```python
import torch

def _softmax(x, axis=-1):
    return torch.softmax(x, dim=axis)
def _gelu(x):
    return torch.nn.functional.gelu(x, approximate="tanh")
def _silu(x):
    return torch.nn.functional.silu(x)
def _sigmoid(x):
    return torch.sigmoid(x)
def _layernorm(x, axis=-1, eps=1e-5):
    m = x.mean(dim=axis, keepdim=True)
    v = x.var(dim=axis, keepdim=True, unbiased=False)
    return (x - m) / torch.sqrt(v + eps)
def _scatter_add(tgt, idx, src, axis=0):
    return tgt.clone().index_add_(axis, idx, src)
def _segment_sum(src, seg, n):
    out = torch.zeros((n,) + src.shape[1:], dtype=src.dtype)
    return out.index_add_(0, seg, src)
def _pad(x, pw):
    flat = tuple(v for pair in reversed(pw) for v in pair)
    return torch.nn.functional.pad(x, flat)

kernel_name = 'gated_mix__spectral_gfnet__ssm_conv_s5__prompt'

def setup_inputs():

    _w = (lambda a: (lambda t: t.to(torch.bfloat16) if t.is_floating_point() else t)(torch.as_tensor(a)))
    def _A_setup():
        B, S, D = 1, 2048, 1024
        Df = D // 2 + 1
        return {
            "x": _w((lambda *s: torch.randn(*s, dtype=torch.bfloat16) * 0.05)(B, S, D)),
            "w_r": _w((lambda *s: torch.randn(*s, dtype=torch.bfloat16) * 0.8)(S, Df) * 0.02),
            "w_i": _w((lambda *s: torch.randn(*s, dtype=torch.bfloat16) * 0.8)(S, Df) * 0.02),
        }
    _A_in = _A_setup()

    def _B_setup():
        B, S, D = 1, 2048, 1024
        P = D
        Lambda_re = -0.5 * (lambda _x: torch.exp(torch.as_tensor(_x)))((lambda *s: torch.randn(*s, dtype=torch.bfloat16) * 0.2)(P))
        Lambda_im = (lambda *s: torch.randn(*s, dtype=torch.bfloat16) * 0.4)(P) * 1.0
        B_re = (lambda *s: torch.randn(*s, dtype=torch.bfloat16) * 0.2)(P, D) * (D ** -0.5)
        B_im = (lambda *s: torch.randn(*s, dtype=torch.bfloat16) * 0.2)(P, D) * (D ** -0.5)
        C_re = (lambda *s: torch.randn(*s, dtype=torch.bfloat16) * 0.2)(D, P) * (P ** -0.5)
        C_im = (lambda *s: torch.randn(*s, dtype=torch.bfloat16) * 0.2)(D, P) * (P ** -0.5)
        log_dt = (lambda *s: torch.randn(*s, dtype=torch.bfloat16) * 0.2)(P) * 0.3 - 2.0
        Dskip = (lambda *s: torch.randn(*s, dtype=torch.bfloat16) * 0.05)(D)
        return {
            "x": _w((lambda *s: torch.randn(*s, dtype=torch.bfloat16) * 0.05)(B, S, D)),
            "Lambda_re": _w(Lambda_re),
            "Lambda_im": _w(Lambda_im),
            "B_re": _w(B_re),
            "B_im": _w(B_im),
            "C_re": _w(C_re),
            "C_im": _w(C_im),
            "log_dt": _w(log_dt),
            "Dskip": _w(Dskip),
        }
    _B_in = _B_setup()

    return {
        "A_x": _A_in["x"],
        "A_w_r": _A_in["w_r"],
        "A_w_i": _A_in["w_i"],
        "B_x": _B_in["x"],
        "B_Lambda_re": _B_in["Lambda_re"],
        "B_Lambda_im": _B_in["Lambda_im"],
        "B_B_re": _B_in["B_re"],
        "B_B_im": _B_in["B_im"],
        "B_C_re": _B_in["C_re"],
        "B_C_im": _B_in["C_im"],
        "B_log_dt": _B_in["log_dt"],
        "B_Dskip": _B_in["Dskip"],
        "gate_w": _w((lambda *s: torch.randn(*s, dtype=torch.bfloat16) * 0.05)(1024) * 16.0),
    }

def reference(A_x, A_w_r, A_w_i, B_x, B_Lambda_re, B_Lambda_im, B_B_re, B_B_im, B_C_re, B_C_im, B_log_dt, B_Dskip, gate_w):
    def _A_ref(x, w_r, w_i):
        B, S, D = x.shape
        X = (lambda x, axes=(-2,-1): torch.fft.rfft2(x.float(), dim=axes))(x, axes=(-2, -1))
        W = w_r + 1j * w_i
        X = X * W
        y = (lambda x, s, axes=(-2,-1): torch.fft.irfft2(x, s=s, dim=axes).to(torch.bfloat16))(X, (S, D), axes=(-2, -1))
        return y

    def _B_ref(x, Lambda_re, Lambda_im, B_re, B_im, C_re, C_im, log_dt, Dskip):
        Bsz, L, H = x.shape
        Lam = Lambda_re + 1j * Lambda_im
        Bmat = B_re + 1j * B_im
        Cmat = C_re + 1j * C_im
        dt = torch.exp(log_dt)
        Lam_bar = torch.exp(dt * Lam)
        B_bar = ((Lam_bar - 1.0) / Lam)[:, None] * Bmat
        Bu = torch.einsum("bld,pd->blp", x + 0j, B_bar)
        h = torch.zeros_like(Bu[:, 0, :])
        hs = []
        for t in range(L):
            h = Lam_bar[None, :] * h + Bu[:, t, :]
            hs.append(h)
        hseq = torch.stack(hs, 1)
        y = 2.0 * torch.einsum("blp,dp->bld", hseq, Cmat).real + x * Dskip[None, None, :]
        return y

    x = A_x
    g = _sigmoid((x * gate_w).sum(-1, keepdims=True))
    a = _A_ref(x, A_w_r, A_w_i)
    b = _B_ref(x, B_Lambda_re, B_Lambda_im, B_B_re, B_B_im, B_C_re, B_C_im, B_log_dt, B_Dskip)
    return g * a + (1 - g) * b
```

```cpp
#include <cuda_runtime.h>
#include <cuda_bf16.h>
#include <cuda.h>
#include <stdint.h>

typedef __nv_bfloat16 bf16;

constexpr int X1_ROWS = 1032;
__device__ __align__(1024) bf16 g_hT[2 * 1024 * 2048];
__device__ __align__(1024) bf16 g_X1[128 * X1_ROWS * 16];
__device__ __align__(1024) bf16 g_A[128 * 2048 * 8];
__device__ __align__(16) float2 g_gate[2048];
__device__ __align__(16) uint4 g_agg[8 * 1024];
__device__ unsigned g_cnt[32 * 32];
constexpr int CNT_P1 = 0, CNT_C = 1, CNT_H = 2  , CNT_A = 10  , CNT_DONE = 18, CNT_EPOCH = 19;
#define PROF(i) do { } while (0)

constexpr int STAGE_BYTES = 49152;
constexpr int NSTAGE = 3;
constexpr int OFF_AUX = NSTAGE * STAGE_BYTES;
constexpr int OFF_X1 = OFF_AUX;
constexpr int OFF_W = OFF_AUX + 32768;
constexpr int W_PITCH = 8704;
constexpr int OFF_CONST = OFF_AUX + 67584;
constexpr int OFF_F64 = OFF_CONST;
constexpr int OFF_TW = OFF_CONST + 8192;
constexpr int OFF_BAR = OFF_CONST + 16384;
constexpr int SMEM_BYTES = OFF_BAR + 128;
constexpr int EX_REG = 258;
constexpr int EX_COL = 8 * EX_REG;
constexpr int BAR_FULL = 0, BAR_REL = 3  , BAR_C = 6, BAR_E = 7, BAR_FREE = 8, BAR_P = 9;

#define DEVI __device__ __forceinline__
constexpr long long SPIN_LIMIT = 4000000000ll;

DEVI uint32_t smem_u32(const void* p) { return (uint32_t)__cvta_generic_to_shared(p); }
DEVI uint64_t gtime() { uint64_t t; asm volatile("mov.u64 %0, %%globaltimer;" : "=l"(t)); return t; }
DEVI void mbar_init(uint32_t bar, uint32_t cnt) { asm volatile("mbarrier.init.shared::cta.b64 [%0], %1;" :: "r"(bar), "r"(cnt) : "memory"); }
DEVI void mbar_expect_tx(uint32_t bar, uint32_t bytes) { asm volatile("mbarrier.arrive.expect_tx.shared::cta.b64 _, [%0], %1;" :: "r"(bar), "r"(bytes) : "memory"); }
DEVI void mbar_arrive(uint32_t bar) { asm volatile("mbarrier.arrive.shared::cta.b64 _, [%0];" :: "r"(bar) : "memory"); }
DEVI uint32_t mapa(uint32_t addr, uint32_t cta) { uint32_t r; asm volatile("mapa.shared::cluster.u32 %0, %1, %2;" : "=r"(r) : "r"(addr), "r"(cta)); return r; }
DEVI void mbar_arrive_remote(uint32_t rbar) { asm volatile("mbarrier.arrive.release.cluster.shared::cluster.b64 _, [%0];" :: "r"(rbar) : "memory"); }
DEVI bool mbar_try(uint32_t bar, uint32_t parity) {
    uint32_t ok;
    asm volatile("{\n.reg .pred p;\nmbarrier.try_wait.parity.shared::cta.b64 p, [%1], %2;\nselp.u32 %0, 1, 0, p;\n}" : "=r"(ok) : "r"(bar), "r"(parity) : "memory");
    return ok;
}
DEVI bool mbar_try_cluster(uint32_t bar, uint32_t parity) {
    uint32_t ok;
    asm volatile("{\n.reg .pred p;\nmbarrier.try_wait.parity.acquire.cluster.shared::cta.b64 p, [%1], %2;\nselp.u32 %0, 1, 0, p;\n}" : "=r"(ok) : "r"(bar), "r"(parity) : "memory");
    return ok;
}
DEVI void mbar_wait(uint32_t bar, uint32_t parity) {
    if (mbar_try(bar, parity)) return;
    long long t0 = clock64();
    while (!mbar_try(bar, parity)) { if (clock64() - t0 > SPIN_LIMIT) __trap(); }
}
DEVI void mbar_wait_cluster(uint32_t bar, uint32_t parity) {
    if (mbar_try_cluster(bar, parity)) return;
    long long t0 = clock64();
    while (!mbar_try_cluster(bar, parity)) { if (clock64() - t0 > SPIN_LIMIT) __trap(); }
}
DEVI void cluster_arrive_relaxed() { asm volatile("barrier.cluster.arrive.relaxed.aligned;" ::: "memory"); }
DEVI void cluster_wait() { asm volatile("barrier.cluster.wait.aligned;" ::: "memory"); }
DEVI void fence_barrier_init() { asm volatile("fence.mbarrier_init.release.cluster;" ::: "memory"); }
DEVI void fence_proxy_async() { asm volatile("fence.proxy.async;" ::: "memory"); }
DEVI void named_sync(int id) { asm volatile("bar.sync %0, 128;" :: "r"(id) : "memory"); }

DEVI void wait_counter(const unsigned* p, unsigned target) {
    long long t0 = clock64();
    while (true) {
        unsigned v;
        asm volatile("ld.acquire.gpu.global.u32 %0, [%1];" : "=r"(v) : "l"(p) : "memory");
        if ((int)(v - target) >= 0) break;
        if (clock64() - t0 > SPIN_LIMIT) __trap();
    }
}
DEVI void signal_counter(unsigned* p) {
    asm volatile("red.release.gpu.global.add.u32 [%0], 1;" :: "l"(p) : "memory");
}

DEVI void tma_load_2d(uint32_t dst, const CUtensorMap* map, uint32_t bar, int c0, int c1) {
    asm volatile("cp.async.bulk.tensor.2d.shared::cluster.global.mbarrier::complete_tx::bytes [%0], [%1, {%3, %4}], [%2];"
        :: "r"(dst), "l"(map), "r"(bar), "r"(c0), "r"(c1) : "memory");
}
DEVI void tma_load_3d(uint32_t dst, const CUtensorMap* map, uint32_t bar, int c0, int c1, int c2) {
    asm volatile("cp.async.bulk.tensor.3d.shared::cluster.global.mbarrier::complete_tx::bytes [%0], [%1, {%3, %4, %5}], [%2];"
        :: "r"(dst), "l"(map), "r"(bar), "r"(c0), "r"(c1), "r"(c2) : "memory");
}
DEVI void tma_load_4d(uint32_t dst, const CUtensorMap* map, uint32_t bar, int c0, int c1, int c2, int c3) {
    asm volatile("cp.async.bulk.tensor.4d.shared::cluster.global.mbarrier::complete_tx::bytes [%0], [%1, {%3, %4, %5, %6}], [%2];"
        :: "r"(dst), "l"(map), "r"(bar), "r"(c0), "r"(c1), "r"(c2), "r"(c3) : "memory");
}
DEVI void tma_store_4d(const CUtensorMap* map, uint32_t src, int c0, int c1, int c2, int c3) {
    asm volatile("cp.async.bulk.tensor.4d.global.shared::cta.bulk_group [%0, {%2, %3, %4, %5}], [%1];"
        :: "l"(map), "r"(src), "r"(c0), "r"(c1), "r"(c2), "r"(c3) : "memory");
}
DEVI void bulk_commit() { asm volatile("cp.async.bulk.commit_group;" ::: "memory"); }
DEVI void bulk_wait0() { asm volatile("cp.async.bulk.wait_group 0;" ::: "memory"); }
DEVI void prefetch_map(const CUtensorMap* map) { asm volatile("prefetch.tensormap [%0];" :: "l"(map) : "memory"); }

DEVI void wgmma_fence() { asm volatile("wgmma.fence.sync.aligned;" ::: "memory"); }
DEVI void wgmma_commit() { asm volatile("wgmma.commit_group.sync.aligned;" ::: "memory"); }
template<int N> DEVI void wgmma_wait() { asm volatile("wgmma.wait_group.sync.aligned %0;" :: "n"(N) : "memory"); }
template<int R> DEVI void reg_alloc() { asm volatile("setmaxnreg.inc.sync.aligned.u32 %0;" :: "n"(R)); }
template<int R> DEVI void reg_dealloc() { asm volatile("setmaxnreg.dec.sync.aligned.u32 %0;" :: "n"(R)); }

DEVI uint64_t make_desc(uint32_t addr, uint32_t lbo, uint32_t sbo) {
    return (uint64_t)((addr & 0x3FFFF) >> 4) | ((uint64_t)(lbo >> 4) << 16) | ((uint64_t)(sbo >> 4) << 32) | (1ull << 62);
}

#define ACC8(a, o) "+f"(a[o+0]), "+f"(a[o+1]), "+f"(a[o+2]), "+f"(a[o+3]), "+f"(a[o+4]), "+f"(a[o+5]), "+f"(a[o+6]), "+f"(a[o+7])
#define ACC32(a, o) ACC8(a, o), ACC8(a, o+8), ACC8(a, o+16), ACC8(a, o+24)

template<int TA, int TB>
DEVI void wgmma_n256(float (&d)[128], uint64_t da, uint64_t db, int scale_d) {
    asm volatile("{\n.reg .pred p;\nsetp.ne.b32 p, %130, 0;\n"
        "wgmma.mma_async.sync.aligned.m64n256k16.f32.bf16.bf16 "
        "{%0, %1, %2, %3, %4, %5, %6, %7, %8, %9, %10, %11, %12, %13, %14, %15, "
        "%16, %17, %18, %19, %20, %21, %22, %23, %24, %25, %26, %27, %28, %29, %30, %31, "
        "%32, %33, %34, %35, %36, %37, %38, %39, %40, %41, %42, %43, %44, %45, %46, %47, "
        "%48, %49, %50, %51, %52, %53, %54, %55, %56, %57, %58, %59, %60, %61, %62, %63, "
        "%64, %65, %66, %67, %68, %69, %70, %71, %72, %73, %74, %75, %76, %77, %78, %79, "
        "%80, %81, %82, %83, %84, %85, %86, %87, %88, %89, %90, %91, %92, %93, %94, %95, "
        "%96, %97, %98, %99, %100, %101, %102, %103, %104, %105, %106, %107, %108, %109, %110, %111, "
        "%112, %113, %114, %115, %116, %117, %118, %119, %120, %121, %122, %123, %124, %125, %126, %127}, "
        "%128, %129, p, 1, 1, %131, %132;\n}\n"
        : ACC32(d, 0), ACC32(d, 32), ACC32(d, 64), ACC32(d, 96)
        : "l"(da), "l"(db), "r"(scale_d), "n"(TA), "n"(TB));
}
template<int SCALE_D>
DEVI void wgmma_rs_n64(float (&d)[32], const uint32_t (&a)[4], uint64_t db) {
    asm volatile("{\n.reg .pred p;\nsetp.ne.b32 p, %37, 0;\n"
        "wgmma.mma_async.sync.aligned.m64n64k16.f32.bf16.bf16 "
        "{%0, %1, %2, %3, %4, %5, %6, %7, %8, %9, %10, %11, %12, %13, %14, %15, "
        "%16, %17, %18, %19, %20, %21, %22, %23, %24, %25, %26, %27, %28, %29, %30, %31}, "
        "{%32, %33, %34, %35}, %36, p, 1, 1, 0;\n}\n"
        : ACC32(d, 0)
        : "r"(a[0]), "r"(a[1]), "r"(a[2]), "r"(a[3]), "l"(db), "n"(SCALE_D));
}
DEVI void ldsm_x4_t(uint32_t (&r)[4], uint32_t addr) {
    asm volatile("ldmatrix.sync.aligned.m8n8.x4.trans.shared.b16 {%0, %1, %2, %3}, [%4];"
        : "=r"(r[0]), "=r"(r[1]), "=r"(r[2]), "=r"(r[3]) : "r"(addr) : "memory");
}
DEVI void stsm_x4_t(uint32_t addr, uint32_t r0, uint32_t r1, uint32_t r2, uint32_t r3) {
    asm volatile("stmatrix.sync.aligned.m8n8.x4.trans.shared.b16 [%0], {%1, %2, %3, %4};"
        :: "r"(addr), "r"(r0), "r"(r1), "r"(r2), "r"(r3) : "memory");
}
DEVI uint32_t movm(uint32_t a) { uint32_t d; asm volatile("movmatrix.sync.aligned.m8n8.trans.b16 %0, %1;" : "=r"(d) : "r"(a)); return d; }
DEVI uint32_t pack2(float lo, float hi) { uint32_t d; asm("cvt.rn.bf16x2.f32 %0, %1, %2;" : "=r"(d) : "f"(hi), "f"(lo)); return d; }
DEVI float bf_lo(uint32_t v) { return __uint_as_float(v << 16); }
DEVI float bf_hi(uint32_t v) { return __uint_as_float(v & 0xffff0000u); }
DEVI float bf_round(float v) { return __bfloat162float(__float2bfloat16_rn(v)); }
DEVI float4 lds128(uint32_t a) { float4 v; asm volatile("ld.shared.v4.f32 {%0, %1, %2, %3}, [%4];" : "=f"(v.x), "=f"(v.y), "=f"(v.z), "=f"(v.w) : "r"(a) : "memory"); return v; }
DEVI void sts128(uint32_t a, float4 v) { asm volatile("st.shared.v4.f32 [%0], {%1, %2, %3, %4};" :: "r"(a), "f"(v.x), "f"(v.y), "f"(v.z), "f"(v.w) : "memory"); }
DEVI float lds_bf16(uint32_t a) { uint16_t v; asm volatile("ld.shared.u16 %0, [%1];" : "=h"(v) : "r"(a) : "memory"); return __uint_as_float((uint32_t)v << 16); }

DEVI float2 cmul(float2 a, float2 b) { return make_float2(fmaf(a.x, b.x, -a.y * b.y), fmaf(a.x, b.y, a.y * b.x)); }
DEVI float2 cfma(float2 a, float2 b, float2 c) { return make_float2(fmaf(a.x, b.x, fmaf(-a.y, b.y, c.x)), fmaf(a.x, b.y, fmaf(a.y, b.x, c.y))); }
DEVI float2 cadd(float2 a, float2 b) { return make_float2(a.x + b.x, a.y + b.y); }
DEVI float2 csub(float2 a, float2 b) { return make_float2(a.x - b.x, a.y - b.y); }
DEVI float2 cmul_mi(float2 a) { return make_float2(a.y, -a.x); }
DEVI float2 cw8_1(float2 a) { const float r = 0.70710678118654752f; return make_float2((a.x + a.y) * r, (a.y - a.x) * r); }
DEVI float2 cw8_3(float2 a) { const float r = 0.70710678118654752f; return make_float2((a.y - a.x) * r, -(a.x + a.y) * r); }

DEVI void fft4(float2& a, float2& b, float2& c, float2& d) {
    float2 s0 = cadd(a, c), s1 = csub(a, c), s2 = cadd(b, d), s3 = cmul_mi(csub(b, d));
    a = cadd(s0, s2); b = cadd(s1, s3); c = csub(s0, s2); d = csub(s1, s3);
}
DEVI void fft8(float2 (&v)[8]) {
    fft4(v[0], v[2], v[4], v[6]);
    fft4(v[1], v[3], v[5], v[7]);
    float2 o0 = v[1], o1 = cw8_1(v[3]), o2 = cmul_mi(v[5]), o3 = cw8_3(v[7]);
    float2 e0 = v[0], e1 = v[2], e2 = v[4], e3 = v[6];
    v[0] = cadd(e0, o0); v[4] = csub(e0, o0);
    v[1] = cadd(e1, o1); v[5] = csub(e1, o1);
    v[2] = cadd(e2, o2); v[6] = csub(e2, o2);
    v[3] = cadd(e3, o3); v[7] = csub(e3, o3);
}
DEVI void fft16(float2 (&v)[16]) {
    const float c1 = 0.92387953251128674f, s1 = 0.38268343236508977f;
#pragma unroll
    for (int i = 0; i < 4; i++) fft4(v[i], v[i + 4], v[i + 8], v[i + 12]);
    v[5] = cmul(v[5], make_float2(c1, -s1));
    v[9] = cw8_1(v[9]);
    v[13] = cmul(v[13], make_float2(s1, -c1));
    v[6] = cw8_1(v[6]);
    v[10] = cmul_mi(v[10]);
    v[14] = cw8_3(v[14]);
    v[7] = cmul(v[7], make_float2(s1, -c1));
    v[11] = cw8_3(v[11]);
    v[15] = cmul(v[15], make_float2(-c1, s1));
#pragma unroll
    for (int a = 0; a < 4; a++) fft4(v[4 * a], v[4 * a + 1], v[4 * a + 2], v[4 * a + 3]);
}
#define F16(k) (4 * ((k) & 3) + ((k) >> 2))

DEVI float2 unit_root(float turns2) {
    float s, c; sincospif(turns2, &s, &c); return make_float2(c, -s);
}
template<int N> DEVI void powers(float2 (&w)[N], float2 w1) {
    w[0] = make_float2(1.f, 0.f); w[1] = w1;
#pragma unroll
    for (int i = 2; i < N; i++) w[i] = cmul(w[i >> 1], w[i - (i >> 1)]);
}

struct Params {
    const bf16 *x, *lam_re, *lam_im, *log_dt, *dskip, *gate_w;
    float* out;
    int swapB;
};

DEVI void helper_gate(const Params& P, int b, int t) {
    const int lane = t & 31, w = t >> 5;
    uint4 gw[4];
#pragma unroll
    for (int i = 0; i < 4; i++) gw[i] = __ldg((const uint4*)P.gate_w + i * 32 + lane);
#pragma unroll 2
    for (int rr = 0; rr < 4; rr++) {
        const int row = 16 * b + 4 * w + rr;
        uint4 xv[4];
#pragma unroll
        for (int i = 0; i < 4; i++) xv[i] = __ldg((const uint4*)(P.x + (size_t)row * 1024) + i * 32 + lane);
        float s = 0.f;
#pragma unroll
        for (int i = 0; i < 4; i++) {
            const uint32_t xa[4] = {xv[i].x, xv[i].y, xv[i].z, xv[i].w}, ga[4] = {gw[i].x, gw[i].y, gw[i].z, gw[i].w};
#pragma unroll
            for (int c = 0; c < 4; c++) {
                __nv_bfloat162 pr = __hmul2(*(const __nv_bfloat162*)&xa[c], *(const __nv_bfloat162*)&ga[c]);
                uint32_t u = *(uint32_t*)&pr;
                s += bf_lo(u) + bf_hi(u);
            }
        }
#pragma unroll
        for (int o = 16; o > 0; o >>= 1) s += __shfl_xor_sync(0xffffffffu, s, o);
        if (lane == 0) {
            s = bf_round(s);
            float g = bf_round(1.f / (1.f + __expf(-s)));
            g_gate[row] = make_float2(g, bf_round(1.f - g));
        }
    }
}

DEVI void helper_mid_passes(float2* ex, int t) {
    const int lo = t & 15;
    float2 tw[16];
    powers<16>(tw, unit_root((float)lo * (1.f / 128.f)));
    float2* reg = ex + (t >> 4) * EX_REG;
#pragma unroll 1
    for (int j = 0; j < 4; j++) {
        float2* e = reg + j * EX_COL;
        float2 v[16];
#pragma unroll
        for (int i = 0; i < 16; i++) v[i] = e[16 * i + lo];
        fft16(v);
        __syncwarp();
        e[lo] = v[0];
#pragma unroll
        for (int k = 1; k < 16; k++) e[16 * k + (lo ^ k)] = cmul(v[F16(k)], tw[k]);
        __syncwarp();
#pragma unroll
        for (int i = 0; i < 16; i++) v[i] = e[16 * lo + (i ^ lo)];
        fft16(v);
        __syncwarp();
#pragma unroll
        for (int k = 0; k < 16; k++) e[16 * k + lo] = v[F16(k)];
    }
}
DEVI int ex_pos(int k) { return (k & 7) * EX_REG + ((k >> 7) << 4) + ((k >> 3) & 15); }

DEVI void helper_p1(const Params& P, int b, int t, float2* ex) {
#pragma unroll 1
    for (int bt = 0; bt < 2; bt++) {
        const int r = t + 128 * bt;
        uint4 xv[8];
#pragma unroll
        for (int n = 0; n < 8; n++) xv[n] = __ldg((const uint4*)(P.x + (size_t)(256 * n + r) * 1024 + 8 * b));
        float2 w[8];
        powers<8>(w, unit_root((float)r * (1.f / 1024.f)));
#pragma unroll
        for (int j = 0; j < 4; j++) {
            float2 v[8];
#pragma unroll
            for (int n = 0; n < 8; n++) {
                const uint32_t u = j == 0 ? xv[n].x : j == 1 ? xv[n].y : j == 2 ? xv[n].z : xv[n].w;
                v[n] = make_float2(bf_lo(u), bf_hi(u));
            }
            fft8(v);
            ex[j * EX_COL + r] = v[0];
#pragma unroll
            for (int k = 1; k < 8; k++) ex[j * EX_COL + k * EX_REG + r] = cmul(v[k], w[k]);
        }
    }
    named_sync(3);
    helper_mid_passes(ex, t);
    named_sync(3);
    uint4* dst = (uint4*)(g_X1 + (size_t)b * X1_ROWS * 16);
#pragma unroll 1
    for (int i = 0; i < 9; i++) {
        const int k = t + 128 * i;
        if (k > 1024) break;
        const int p0 = ex_pos(k), p1 = ex_pos((2048 - k) & 2047);
        uint32_t re[4], im[4];
#pragma unroll
        for (int j = 0; j < 4; j++) {
            const float2 a = ex[j * EX_COL + p0], c = ex[j * EX_COL + p1];
            re[j] = pack2(a.x + c.x, a.y + c.y);
            im[j] = pack2(a.y - c.y, c.x - a.x);
        }
        dst[2 * k] = make_uint4(re[0], re[1], re[2], re[3]);
        dst[2 * k + 1] = make_uint4(im[0], im[1], im[2], im[3]);
    }
}

DEVI void helper_p3(int b, int t, float2* ex) {
    const uint4* src = (const uint4*)(g_X1 + (size_t)b * X1_ROWS * 16);
#pragma unroll 1
    for (int i0 = 0; i0 < 9; i0 += 3) {
        uint4 vr[3], vi[3];
#pragma unroll
        for (int i = 0; i < 3; i++) {
            const int k = t + 128 * (i0 + i);
            if (k <= 1024) { vr[i] = __ldcg(src + 2 * k); vi[i] = __ldcg(src + 2 * k + 1); }
        }
#pragma unroll
        for (int i = 0; i < 3; i++) {
            const int k = t + 128 * (i0 + i);
            if (k <= 1024) {
                if ((k & 1023) == 0) vi[i] = make_uint4(0, 0, 0, 0);
                const int p0 = ex_pos(k), p1 = ex_pos((2048 - k) & 2047);
                const uint32_t re[4] = {vr[i].x, vr[i].y, vr[i].z, vr[i].w}, im[4] = {vi[i].x, vi[i].y, vi[i].z, vi[i].w};
#pragma unroll
                for (int j = 0; j < 4; j++) {
                    const float ar = bf_lo(re[j]), br = bf_hi(re[j]), ai = bf_lo(im[j]), bi = bf_hi(im[j]);
                    ex[j * EX_COL + p0] = make_float2(ai + br, ar - bi);
                    ex[j * EX_COL + p1] = make_float2(br - ai, ar + bi);
                }
            }
        }
    }
    named_sync(3);
    helper_mid_passes(ex, t);
    named_sync(3);
    uint4* dst = (uint4*)(g_A + (size_t)b * 2048 * 8);
#pragma unroll 1
    for (int bt = 0; bt < 2; bt++) {
        const int r = t + 128 * bt;
        float2 w[8];
        powers<8>(w, unit_root((float)r * (1.f / 1024.f)));
        uint32_t o[8][4];
#pragma unroll
        for (int j = 0; j < 4; j++) {
            float2 v[8];
            v[0] = ex[j * EX_COL + r];
#pragma unroll
            for (int k = 1; k < 8; k++) v[k] = cmul(ex[j * EX_COL + k * EX_REG + r], w[k]);
            fft8(v);
#pragma unroll
            for (int n = 0; n < 8; n++) o[n][j] = pack2(v[n].y, v[n].x);
        }
#pragma unroll
        for (int n = 0; n < 8; n++) dst[256 * n + r] = make_uint4(o[n][0], o[n][1], o[n][2], o[n][3]);
    }
}

DEVI void helper_tables(uint8_t* sm, int t) {
    {
        const int n = t >> 1, cn = n >> 5, bn = n & 31, c = t & 1;
#pragma unroll 1
        for (int ch = 0; ch < 4; ch++) {
            uint32_t u[4];
#pragma unroll
            for (int i = 0; i < 4; i++) {
                float f[2];
#pragma unroll
                for (int e = 0; e < 2; e++) {
                    const int a = ch * 8 + 2 * i + e;
                    float s, co; sincospif((float)((a * bn) & 31) * (1.f / 16.f), &s, &co);
                    f[e] = (c == cn) ? co : (c ? s : -s);
                }
                u[i] = pack2(f[0], f[1]);
            }
            *(uint4*)(sm + OFF_F64 + n * 128 + (((c * 4 + ch) ^ (n & 7)) << 4)) = make_uint4(u[0], u[1], u[2], u[3]);
        }
    }
#pragma unroll 1
    for (int i = 0; i < 4; i++) {
        const int idx = t + 128 * i, lane = idx & 31, u = idx >> 5;
        const int row = (u >> 2) * 8 + (lane >> 2), col = (u & 3) * 8 + (lane & 3) * 2;
        const float2 w0 = unit_root((float)(row * col) * (1.f / 512.f)), w1 = unit_root((float)(row * (col + 1)) * (1.f / 512.f));
        *(float4*)(sm + OFF_TW + idx * 16) = make_float4(w0.x, w0.y, w1.x, w1.y);
    }
}

DEVI void helper_eprep(const Params& P, int b, int t, uint32_t sb) {
    const int mt = b >> 3, cb0 = (b & 7) * 16;
    const int g = t & 7, jl = (t >> 3) & 3, w = t >> 5;
    const int j = w * 4 + jl, cb = cb0 + j;
    const uint4 dk = __ldg((const uint4*)P.dskip + cb);
    const uint32_t dka[4] = {dk.x, dk.y, dk.z, dk.w};
#pragma unroll 1
    for (int u0 = 0; u0 < 8; u0 += 2) {
        uint4 av[2][2], xv[2][2]; float2 gt[2][2];
#pragma unroll
        for (int uu = 0; uu < 2; uu++) {
            const int u = u0 + uu;
#pragma unroll
            for (int hh = 0; hh < 2; hh++) {
                const int tt = 256 * (mt >> 1) + 64 * (2 * (u & 1) + hh) + 8 * (4 * (mt & 1) + (u >> 1)) + g;
                av[uu][hh] = __ldcg((const uint4*)g_A + (size_t)cb * 2048 + tt);
                xv[uu][hh] = __ldg((const uint4*)(P.x + (size_t)tt * 1024) + cb);
                gt[uu][hh] = __ldcg(&g_gate[tt]);
            }
        }
#pragma unroll
        for (int uu = 0; uu < 2; uu++) {
            float ev[2][8];
#pragma unroll
            for (int hh = 0; hh < 2; hh++) {
                const uint32_t aa[4] = {av[uu][hh].x, av[uu][hh].y, av[uu][hh].z, av[uu][hh].w};
                const uint32_t xa[4] = {xv[uu][hh].x, xv[uu][hh].y, xv[uu][hh].z, xv[uu][hh].w};
#pragma unroll
                for (int q = 0; q < 4; q++) {
                    __nv_bfloat162 pr = __hmul2(*(const __nv_bfloat162*)&xa[q], *(const __nv_bfloat162*)&dka[q]);
                    const uint32_t pu = *(uint32_t*)&pr;
                    const uint32_t ga = pack2(gt[uu][hh].x * bf_lo(aa[q]), gt[uu][hh].x * bf_hi(aa[q]));
                    ev[hh][2 * q] = fmaf(gt[uu][hh].y, bf_lo(pu), bf_lo(ga));
                    ev[hh][2 * q + 1] = fmaf(gt[uu][hh].y, bf_hi(pu), bf_hi(ga));
                }
            }
            const uint32_t dst = sb + OFF_AUX + j * 4096 + ((u0 + uu) * 32 + g * 4) * 16;
#pragma unroll
            for (int q = 0; q < 4; q++) sts128(dst + q * 16, make_float4(ev[0][2 * q], ev[0][2 * q + 1], ev[1][2 * q], ev[1][2 * q + 1]));
        }
    }
}

DEVI void c_mm(float (&acc)[2][32], const uint32_t (&a)[2][4][4], uint64_t df) {
    wgmma_fence();
#pragma unroll
    for (int h = 0; h < 2; h++) {
        wgmma_rs_n64<0>(acc[h], a[h][0], df);
        wgmma_rs_n64<1>(acc[h], a[h][1], df + 2);
        wgmma_rs_n64<1>(acc[h], a[h][2], df + 4);
        wgmma_rs_n64<1>(acc[h], a[h][3], df + 6);
    }
    wgmma_commit();
    wgmma_wait<0>();
}
DEVI void c_twiddle_transpose(const float (&acc)[2][32], uint32_t (&a)[2][4][4], uint32_t tw_addr) {
#pragma unroll
    for (int h = 0; h < 2; h++)
#pragma unroll
        for (int hh = 0; hh < 2; hh++)
#pragma unroll
            for (int j = 0; j < 4; j++) {
                const float4 w = lds128(tw_addr + ((h * 2 + hh) * 4 + j) * 512);
                const float2 v0 = cmul(make_float2(acc[h][4 * j + 2 * hh], acc[h][16 + 4 * j + 2 * hh]), make_float2(w.x, w.y));
                const float2 v1 = cmul(make_float2(acc[h][4 * j + 2 * hh + 1], acc[h][16 + 4 * j + 2 * hh + 1]), make_float2(w.z, w.w));
                a[j >> 1][h][2 * hh + (j & 1)] = movm(pack2(v0.x, v1.x));
                a[j >> 1][2 + h][2 * hh + (j & 1)] = movm(pack2(v0.y, v1.y));
            }
}
DEVI uint32_t swz(uint32_t a) { return a ^ ((a >> 3) & 0x70); }

DEVI void phase_c(uint32_t sb, int b, int warp, int lane) {
    const int g = lane >> 2, q = lane & 3;
    const uint64_t df = make_desc(sb + OFF_F64, 16, 1024);
    const uint32_t tw_addr = sb + OFF_TW + lane * 16;
    uint32_t a[2][4][4];
    float acc[2][32];
    const uint32_t xrow = sb + OFF_X1 + (warp >> 2) * 16384 + ((lane >> 3) & 1) * 4096 + ((lane >> 4) * 8 + (lane & 7)) * 128;
    const uint32_t ch0 = (((warp & 3) * 2) ^ (lane & 7)) << 4, ch1 = (((warp & 3) * 2 + 1) ^ (lane & 7)) << 4;
#pragma unroll
    for (int h = 0; h < 2; h++)
#pragma unroll
        for (int s = 0; s < 4; s++) ldsm_x4_t(a[h][s], xrow + h * 8192 + (s & 1) * 2048 + ((s >> 1) ? ch1 : ch0));
    c_mm(acc, a, df);
    c_twiddle_transpose(acc, a, tw_addr);
    c_mm(acc, a, df);
    {
        const uint32_t dbase = OFF_W + ((16 * b) & 127) + 1026 * warp;
        uint32_t mbase = OFF_W + W_PITCH + ((1026 * (2041 - 8 * b)) & 127) + 1026 * (7 - warp);
        if (b == 0 && warp == 0) mbase = dbase;
        const float sc = 1.f / 4194304.f;
#pragma unroll
        for (int h = 0; h < 2; h++)
#pragma unroll
            for (int j = 0; j < 4; j++)
#pragma unroll
                for (int hh = 0; hh < 2; hh++) {
                    float2 r[2];
#pragma unroll
                    for (int e = 0; e < 2; e++) {
                        const int m = 16 * h + 8 * hh + g + 32 * (8 * j + 2 * q + e);
                        const uint32_t ad = sb + swz(j < 2 ? dbase + 2 * m : mbase + 2 * (1024 - m));
                        float wr = lds_bf16(ad), wi = lds_bf16(ad + 2 * W_PITCH);
                        if (j >= 2) wi = -wi;
                        if (h == 0 && hh == 0 && e == 0 && (j == 0 || j == 2)) {
                            if (lane == 0) {
                                const uint32_t a2 = sb + swz(j == 0 ? mbase : dbase + 1024);
                                const float ur = lds_bf16(a2), ui = lds_bf16(a2 + 2 * W_PITCH);
                                wr = 0.5f * (wr + ur);
                                wi = 0.5f * (wi + (j == 0 ? -ui : ui));
                            }
                        }
                        r[e] = cmul(make_float2(acc[h][4 * j + 2 * hh + e], acc[h][16 + 4 * j + 2 * hh + e]), make_float2(wr * sc, wi * sc));
                    }
                    a[h][j >> 1][2 * (j & 1) + hh] = pack2(r[0].y, r[1].y);
                    a[h][2 + (j >> 1)][2 * (j & 1) + hh] = pack2(r[0].x, r[1].x);
                }
    }
    c_mm(acc, a, df);
    c_twiddle_transpose(acc, a, tw_addr);
    c_mm(acc, a, df);
#pragma unroll
    for (int h = 0; h < 2; h++)
#pragma unroll
        for (int s = 0; s < 4; s++) {
            const float* v = &acc[h][8 * s];
            stsm_x4_t(xrow + h * 8192 + (s & 1) * 2048 + ((s >> 1) ? ch0 : ch1),
                      pack2(v[0], v[1]), pack2(v[2], v[3]), pack2(v[4], v[5]), pack2(v[6], v[7]));
        }
}

__global__ void __cluster_dims__(2, 1, 1) __launch_bounds__(384, 1)
fused_kernel(const __grid_constant__ CUtensorMap mapB, const __grid_constant__ CUtensorMap mapX,
             const __grid_constant__ CUtensorMap mapH, const __grid_constant__ CUtensorMap mapCre,
             const __grid_constant__ CUtensorMap mapCim, const __grid_constant__ CUtensorMap mapX1,
             const __grid_constant__ CUtensorMap mapWr, const __grid_constant__ CUtensorMap mapWi,
             const __grid_constant__ Params P) {
    extern __shared__ __align__(1024) uint8_t sm[];
    const uint32_t sb = smem_u32(sm);
    const uint32_t bars = sb + OFF_BAR;
    const int b = blockIdx.x, tid = threadIdx.x, warp = tid >> 5, lane = tid & 31;
    const bool main_cta = b < 128;
    if (b == 129) return;
    unsigned epoch;
    asm volatile("ld.volatile.global.u32 %0, [%1];" : "=r"(epoch) : "l"(&g_cnt[CNT_EPOCH * 32]));

    auto issue_loads = [&](int it) {
        const int s = it % NSTAGE;
        const uint32_t full = bars + 8 * (BAR_FULL + s), st = sb + s * STAGE_BYTES;
        mbar_expect_tx(full, STAGE_BYTES);
        if (it < 16) {
            tma_load_4d(st, &mapB, full, it * 64, 0, 0, (b & 15) * 8);
            tma_load_4d(st + 16384, &mapX, full, it * 64, 0, 0, (b >> 4) * 128);
        } else {
            const int k = it - 16, nt = (b >> 1) & 3, ks = b & 1;
            const CUtensorMap* mc = ks ? &mapCim : &mapCre;
            if (k >= NSTAGE) tma_load_3d(st, &mapH, full, 0, ks * 1024 + k * 64, (b >> 3) * 2);
            tma_load_2d(st + 16384, mc, full, k * 64, nt * 256 + ks * 128);
            tma_load_2d(st + 32768, mc, full, k * 64, nt * 256 + (ks ^ 1) * 128);
        }
    };
    auto release_stage = [&](int it) {
        unsigned old;
        asm volatile("atom.acq_rel.cta.shared.add.u32 %0, [%1], 1;" : "=r"(old) : "r"(bars + 8 * (BAR_REL + it % NSTAGE)) : "memory");
        if ((old & 7) == 7) {
            if (it + NSTAGE < 32) issue_loads(it + NSTAGE);
            else if (it == 29) mbar_arrive_remote(mapa(bars + 8 * BAR_FREE, (b & 1) ^ 1));
        }
    };

    if (tid == 256) {
        PROF(0);
        if (sb & 1023) __trap();
        for (int s = 0; s < NSTAGE; s++) { mbar_init(bars + 8 * (BAR_FULL + s), 1); *(unsigned*)(sm + OFF_BAR + 8 * (BAR_REL + s)) = 0; }
        mbar_init(bars + 8 * BAR_C, 1); mbar_init(bars + 8 * BAR_E, 128); mbar_init(bars + 8 * BAR_FREE, 1); mbar_init(bars + 8 * BAR_P, 1);
        fence_barrier_init();
        fence_proxy_async();
        if (main_cta) for (int it = 0; it < NSTAGE; it++) issue_loads(it);
        mbar_expect_tx(bars + 8 * BAR_P, 65536);
    }
    __syncthreads();
    if (main_cta) cluster_arrive_relaxed();
    epoch += 1;

    if (warp >= 8) {
        reg_dealloc<104>();
        const int t = tid - 256;
        float2* ex = (float2*)(sm + OFF_AUX);
        if (main_cta) {
            helper_gate(P, b, t);
            if (t == 0) PROF(8);
            helper_p1(P, b, t, ex);
            fence_proxy_async();
            named_sync(3);
            if (t == 0) { signal_counter(&g_cnt[CNT_P1 * 32]); PROF(9); }
        }
        helper_tables(sm, t);
        fence_proxy_async();
        named_sync(3);
        if (t == 0) {
            const uint32_t bc = bars + 8 * BAR_C;
            mbar_expect_tx(bc, 32768 + 4 * 8448);
            const int r0 = (8208 * b) >> 7, r1 = (1026 * (2041 - 8 * b)) >> 7;
            tma_load_2d(sb + OFF_W, &mapWr, bc, 0, r0);
            tma_load_2d(sb + OFF_W + W_PITCH, &mapWr, bc, 0, r1);
            tma_load_2d(sb + OFF_W + 2 * W_PITCH, &mapWi, bc, 0, r0);
            tma_load_2d(sb + OFF_W + 3 * W_PITCH, &mapWi, bc, 0, r1);
            wait_counter(&g_cnt[CNT_P1 * 32], epoch * 128);
            fence_proxy_async();
            PROF(10);
            tma_load_4d(sb + OFF_X1, &mapX1, bc, 0, 0, 0, 2 * b);
            tma_load_4d(sb + OFF_X1 + 16384, &mapX1, bc, 0, 0, 0, 2 * b + 1);
        }
        if (main_cta) {
            if (t == 0) {
                wait_counter(&g_cnt[(CNT_H + (b >> 4)) * 32], epoch * 32);
                fence_proxy_async();
                PROF(1);
                for (int k = 0; k < NSTAGE; k++) {
                    const int s = (16 + k) % NSTAGE;
                    tma_load_3d(sb + s * STAGE_BYTES, &mapH, bars + 8 * (BAR_FULL + s), 0, (b & 1) * 1024 + k * 64, (b >> 3) * 2);
                }
                wait_counter(&g_cnt[CNT_C * 32], epoch * 258);
                PROF(11);
            }
            named_sync(3);
            helper_p3(b, t, ex);
            named_sync(3);
            if (t == 0) {
                signal_counter(&g_cnt[(CNT_A + (b >> 4)) * 32]);
                PROF(12);
                wait_counter(&g_cnt[(CNT_A + (b & 7)) * 32], epoch * 16);
                PROF(13);
            }
            named_sync(3);
            helper_eprep(P, b, t, sb);
            mbar_arrive(bars + 8 * BAR_E);
            if (t == 0) PROF(14);
            cluster_wait();
        }
    } else {
        reg_alloc<200>();
        const int wg = warp >> 2, wi = warp & 3, g = lane >> 2, q = lane & 3;
        const int tw = tid & 127;
        if (main_cta) {
            float acc[128];
            const int pt = b & 15, tc = b >> 4;
            const int p = pt * 64 + wg * 32 + wi * 8 + g;
            float2 lam1, lam32, lam64, lam128, wq, w4, l64q, coef;
            {
                const float lr = __bfloat162float(P.lam_re[p]), li = __bfloat162float(P.lam_im[p]);
                const float dt = bf_round(expf(__bfloat162float(P.log_dt[p])));
                const float mag = expf(dt * lr);
                float sn, cs; sincosf(dt * li, &sn, &cs);
                lam1 = make_float2(mag * cs, mag * sn);
                const float inv = 1.f / (lr * lr + li * li);
                coef = cmul(make_float2(lam1.x - 1.f, lam1.y), make_float2(lr * inv, -li * inv));
                if (P.swapB) { lam1.y = -lam1.y; coef.y = -coef.y; }
                float2 z = lam1;
#pragma unroll
                for (int i = 0; i < 5; i++) z = cmul(z, z);
                lam32 = z; lam64 = cmul(z, z); lam128 = cmul(lam64, lam64);
                const float2 l256 = cmul(lam128, lam128), l512 = cmul(l256, l256);
                w4 = cmul(l512, l512);
                const float2 one = make_float2(1.f, 0.f);
                wq = cmul((q & 1) ? l256 : one, (q & 2) ? l512 : one);
                l64q = cmul((q & 1) ? lam64 : one, (q & 2) ? lam128 : one);
            }
            for (int it = 0; it < 16; it++) {
                const int s = it % NSTAGE;
                mbar_wait(bars + 8 * (BAR_FULL + s), (it / NSTAGE) & 1);
                if (it == 0 && tid == 0) PROF(2);
                const uint32_t st = sb + s * STAGE_BYTES;
                const uint64_t da = make_desc(st + wg * 8192, 16, 1024), db = make_desc(st + 16384, 16, 1024);
                wgmma_fence();
#pragma unroll
                for (int j = 0; j < 4; j++) wgmma_n256<0, 0>(acc, da + 2 * j, db + 2 * j, (it | j) != 0);
                wgmma_commit();
                if (it > 0) {
                    wgmma_wait<1>();
                    if (lane == 0) release_stage(it - 1);
                    __syncwarp();
                }
            }
            wgmma_wait<0>();
            if (lane == 0) release_stage(15);
            __syncwarp();
            if (tid == 0) PROF(3);
            float2 lo = make_float2(acc[0], acc[2]), hi = make_float2(acc[64], acc[66]);
#pragma unroll
            for (int t = 1; t < 32; t++) {
                const int i = 4 * (t >> 1) + (t & 1);
                lo = cfma(lam1, lo, make_float2(acc[i], acc[i + 2]));
                hi = cfma(lam1, hi, make_float2(acc[64 + i], acc[66 + i]));
            }
            float2 v = cfma(lam32, lo, hi);
            {
                float2 n = make_float2(__shfl_up_sync(0xffffffffu, v.x, 1, 4), __shfl_up_sync(0xffffffffu, v.y, 1, 4));
                if (q >= 1) v = cfma(lam64, n, v);
                n = make_float2(__shfl_up_sync(0xffffffffu, v.x, 2, 4), __shfl_up_sync(0xffffffffu, v.y, 2, 4));
                if (q >= 2) v = cfma(lam128, n, v);
            }
            if (q == 3 && tc < 7) {
                asm volatile("st.volatile.global.v4.u32 [%0], {%1, %2, %3, %4};"
                    :: "l"(&g_agg[tc * 1024 + p]), "r"(__float_as_uint(v.x)), "r"(epoch), "r"(__float_as_uint(v.y)), "r"(epoch) : "memory");
            }
            float2 ex = make_float2(__shfl_up_sync(0xffffffffu, v.x, 1, 4), __shfl_up_sync(0xffffffffu, v.y, 1, 4));
            if (q == 0) ex = make_float2(0.f, 0.f);
#pragma unroll
            for (int i = 0; i < 128; i += 4) {
                const float2 u0 = cmul(coef, make_float2(acc[i], acc[i + 2])), u1 = cmul(coef, make_float2(acc[i + 1], acc[i + 3]));
                acc[i] = u0.x; acc[i + 2] = u0.y; acc[i + 1] = u1.x; acc[i + 3] = u1.y;
            }
            {
                float2 part = make_float2(0.f, 0.f);
                const int c0 = tc - 1 - q, c1 = tc - 5 - q;
                if (c0 >= 0) {
                    uint4 r0, r1 = make_uint4(0, epoch, 0, epoch);
                    long long t0 = clock64();
                    while (true) {
                        asm volatile("ld.volatile.global.v4.u32 {%0, %1, %2, %3}, [%4];" : "=r"(r0.x), "=r"(r0.y), "=r"(r0.z), "=r"(r0.w) : "l"(&g_agg[c0 * 1024 + p]) : "memory");
                        if (c1 >= 0) asm volatile("ld.volatile.global.v4.u32 {%0, %1, %2, %3}, [%4];" : "=r"(r1.x), "=r"(r1.y), "=r"(r1.z), "=r"(r1.w) : "l"(&g_agg[c1 * 1024 + p]) : "memory");
                        if (r0.y == epoch && r0.w == epoch && r1.y == epoch && r1.w == epoch) break;
                        if (clock64() - t0 > SPIN_LIMIT) __trap();
                    }
                    part = cfma(w4, make_float2(__uint_as_float(r1.x), __uint_as_float(r1.z)), make_float2(__uint_as_float(r0.x), __uint_as_float(r0.z)));
                    part = cmul(wq, part);
                }
                __syncwarp();
                part.x += __shfl_xor_sync(0xffffffffu, part.x, 1); part.y += __shfl_xor_sync(0xffffffffu, part.y, 1);
                part.x += __shfl_xor_sync(0xffffffffu, part.x, 2); part.y += __shfl_xor_sync(0xffffffffu, part.y, 2);
                ex = cfma(l64q, part, ex);
            }
            if (tid == 0) PROF(4);
            float2 h0 = cmul(coef, ex), h1 = cmul(coef, cfma(lam32, ex, lo));
            {
                uint4* dre = (uint4*)(g_hT + (size_t)(P.swapB ? 1024 + p : p) * 2048 + tc * 256 + q * 8);
                uint4* dim = (uint4*)(g_hT + (size_t)(P.swapB ? p : 1024 + p) * 2048 + tc * 256 + q * 8);
#pragma unroll
                for (int i = 0; i < 4; i++) {
                    uint32_t r0[4], i0[4], r1[4], i1[4];
#pragma unroll
                    for (int jj = 0; jj < 4; jj++) {
                        const int o = 16 * i + 4 * jj;
                        const float2 a0 = cfma(lam1, h0, make_float2(acc[o], acc[o + 2]));
                        const float2 a1 = cfma(lam1, h1, make_float2(acc[64 + o], acc[66 + o]));
                        h0 = cfma(lam1, a0, make_float2(acc[o + 1], acc[o + 3]));
                        h1 = cfma(lam1, a1, make_float2(acc[65 + o], acc[67 + o]));
                        r0[jj] = pack2(a0.x, h0.x); i0[jj] = pack2(a0.y, h0.y);
                        r1[jj] = pack2(a1.x, h1.x); i1[jj] = pack2(a1.y, h1.y);
                    }
                    dre[4 * i] = make_uint4(r0[0], r0[1], r0[2], r0[3]);
                    dim[4 * i] = make_uint4(i0[0], i0[1], i0[2], i0[3]);
                    dre[4 * i + 16] = make_uint4(r1[0], r1[1], r1[2], r1[3]);
                    dim[4 * i + 16] = make_uint4(i1[0], i1[1], i1[2], i1[3]);
                }
            }
            fence_proxy_async();
            named_sync(1 + wg);
            if (tw == 0) signal_counter(&g_cnt[(CNT_H + tc) * 32]);
            if (tid == 0) PROF(5);
        }
        mbar_wait(bars + 8 * BAR_C, 0);
        if (tid == 0) PROF(6);
        phase_c(sb, b, warp, lane);
        fence_proxy_async();
        named_sync(1 + wg);
        if (tw == 0) {
            tma_store_4d(&mapX1, sb + OFF_X1 + wg * 16384, 0, 0, 0, 2 * b + wg);
            bulk_commit();
            bulk_wait0();
            fence_proxy_async();
            signal_counter(&g_cnt[CNT_C * 32]);
        }
        if (tid == 0) PROF(7);
        if (main_cta) {
            float acc[128];
            const int mt = b >> 3, nt = (b >> 1) & 3, ks = b & 1;
            const int trow = 256 * (mt >> 1) + 128 * (wi & 1) + 8 * (4 * (mt & 1) + 2 * wg + (wi >> 1)) + g;
            const float sg = ks ? -2.f : 2.f;
            const float s0 = sg * __ldcg(&g_gate[trow]).y, s1 = sg * __ldcg(&g_gate[trow + 64]).y;
            cluster_wait();
            for (int k = 0; k < 16; k++) {
                const int it = 16 + k, s = it % NSTAGE;
                mbar_wait(bars + 8 * (BAR_FULL + s), (it / NSTAGE) & 1);
                if (k == 0 && tid == 0) PROF(16);
                const uint32_t st = sb + s * STAGE_BYTES;
                const uint64_t da = make_desc(st + wg * 8192, 8192, 1024), db = make_desc(st + 16384, 16, 1024);
                wgmma_fence();
#pragma unroll
                for (int j = 0; j < 4; j++) wgmma_n256<1, 0>(acc, da + 128 * j, db + 2 * j, (k | j) != 0);
                wgmma_commit();
                if (k > 0) {
                    wgmma_wait<1>();
                    if (lane == 0) release_stage(it - 1);
                    __syncwarp();
                }
            }
            wgmma_wait<0>();
            if (tid == 0) PROF(17);
            mbar_wait_cluster(bars + 8 * BAR_FREE, 0);
            {
                const uint32_t rbar = mapa(bars + 8 * BAR_P, ks ^ 1);
                const uint32_t r0 = mapa(sb + 2 * STAGE_BYTES + tid * 16, ks ^ 1), r1 = mapa(sb + OFF_CONST + tid * 16, ks ^ 1);
#pragma unroll
                for (int j = 0; j < 16; j++) {
                    const uint32_t dst = j < 12 ? r0 + j * 4096 : r1 + (j - 12) * 4096;
                    asm volatile("st.async.weak.shared::cluster.mbarrier::complete_tx::bytes.v4.f32 [%0], {%1, %2, %3, %4}, [%5];"
                        :: "r"(dst), "f"(acc[64 + 4 * j]), "f"(acc[65 + 4 * j]), "f"(acc[66 + 4 * j]), "f"(acc[67 + 4 * j]), "r"(rbar) : "memory");
                }
            }
            mbar_wait(bars + 8 * BAR_E, 0);
#pragma unroll
            for (int j = 0; j < 16; j++) {
                const float4 e = lds128(sb + OFF_AUX + j * 4096 + tid * 16);
                acc[4 * j] = fmaf(s0, acc[4 * j], e.x); acc[4 * j + 1] = fmaf(s0, acc[4 * j + 1], e.y);
                acc[4 * j + 2] = fmaf(s1, acc[4 * j + 2], e.z); acc[4 * j + 3] = fmaf(s1, acc[4 * j + 3], e.w);
            }
            mbar_wait_cluster(bars + 8 * BAR_P, 0);
            if (tid == 0) PROF(18);
            float* o0 = P.out + (size_t)trow * 1024 + nt * 256 + ks * 128 + 2 * q;
#pragma unroll
            for (int j = 0; j < 16; j++) {
                const float4 r = lds128((j < 12 ? sb + 2 * STAGE_BYTES + j * 4096 : sb + OFF_CONST + (j - 12) * 4096) + tid * 16);
                *(float2*)(o0 + 8 * j) = make_float2(fmaf(-s0, r.x, acc[4 * j]), fmaf(-s0, r.y, acc[4 * j + 1]));
                *(float2*)(o0 + 64 * 1024 + 8 * j) = make_float2(fmaf(-s1, r.z, acc[4 * j + 2]), fmaf(-s1, r.w, acc[4 * j + 3]));
            }
            if (tid == 0) PROF(19);
        }
        if (tid == 0) {
            const unsigned old = atomicAdd(&g_cnt[CNT_DONE * 32], 1u);
            if (old == 128) { g_cnt[CNT_DONE * 32] = 0; g_cnt[CNT_EPOCH * 32] = epoch; }
        }
    }
}

typedef CUresult (*PFN_encodeTiled)(CUtensorMap*, CUtensorMapDataType, cuuint32_t, void*, const cuuint64_t*, const cuuint64_t*,
                                    const cuuint32_t*, const cuuint32_t*, CUtensorMapInterleave, CUtensorMapSwizzle,
                                    CUtensorMapL2promotion, CUtensorMapFloatOOBfill);

static CUtensorMap make_map(PFN_encodeTiled enc, const void* ptr, int rank, const cuuint64_t* dims, const cuuint64_t* strides, const cuuint32_t* box) {
    CUtensorMap m;
    cuuint32_t es[5] = {1, 1, 1, 1, 1};
    enc(&m, CU_TENSOR_MAP_DATA_TYPE_BFLOAT16, rank, (void*)ptr, dims, strides, box, es, CU_TENSOR_MAP_INTERLEAVE_NONE,
        CU_TENSOR_MAP_SWIZZLE_128B, CU_TENSOR_MAP_L2_PROMOTION_L2_128B, CU_TENSOR_MAP_FLOAT_OOB_FILL_NONE);
    return m;
}

extern "C" void kernel_launch(void* const* d_in, const int* in_sizes, int n_in, void* d_out, int out_size) {
    const bf16* x = (const bf16*)d_in[0];
    const bf16* wr = (const bf16*)d_in[1];
    const bf16* wi = (const bf16*)d_in[2];
    const bf16* Bre = (const bf16*)d_in[6];
    const bf16* Bim = (const bf16*)d_in[7];
    const bf16* Cre = (const bf16*)d_in[8];
    const bf16* Cim = (const bf16*)d_in[9];

    void* fn = nullptr;
    cudaDriverEntryPointQueryResult st;
    cudaGetDriverEntryPoint("cuTensorMapEncodeTiled", &fn, cudaEnableDefault, &st);
    PFN_encodeTiled enc = (PFN_encodeTiled)fn;
    void *p_hT, *p_X1;
    cudaGetSymbolAddress(&p_hT, g_hT);
    cudaGetSymbolAddress(&p_X1, g_X1);

    Params P;
    P.x = x; P.lam_re = (const bf16*)d_in[4]; P.lam_im = (const bf16*)d_in[5]; P.log_dt = (const bf16*)d_in[10];
    P.dskip = (const bf16*)d_in[11]; P.gate_w = (const bf16*)d_in[12]; P.out = (float*)d_out;
    P.swapB = Bim < Bre;

    CUtensorMap mB, mX, mH, mCre, mCim, mX1, mWr, mWi;
    {
        const bf16* lo = P.swapB ? Bim : Bre; const bf16* hi = P.swapB ? Bre : Bim;
        cuuint64_t d[4] = {1024, 8, 2, 128}, s[3] = {2048, (cuuint64_t)((const char*)hi - (const char*)lo), 16384};
        cuuint32_t bx[4] = {64, 8, 2, 8};
        mB = make_map(enc, lo, 4, d, s, bx);
    }
    {
        cuuint64_t d[4] = {1024, 2, 4, 928}, s[3] = {2048, 64 * 2048, 2 * 2048};
        cuuint32_t bx[4] = {64, 2, 4, 32};
        mX = make_map(enc, x, 4, d, s, bx);
    }
    {
        cuuint64_t d[3] = {64, 2048, 32}, s[2] = {4096, 128};
        cuuint32_t bx[3] = {64, 64, 2};
        mH = make_map(enc, p_hT, 3, d, s, bx);
    }
    {
        cuuint64_t d[2] = {1024, 1024}, s[1] = {2048};
        cuuint32_t bx[2] = {64, 128};
        mCre = make_map(enc, Cre, 2, d, s, bx);
        mCim = make_map(enc, Cim, 2, d, s, bx);
    }
    {
        cuuint64_t d[4] = {64, 32, 4, X1_ROWS / 4}, s[3] = {4 * X1_ROWS * 32, X1_ROWS * 32, 128};
        cuuint32_t bx[4] = {64, 32, 4, 1};
        mX1 = make_map(enc, p_X1, 4, d, s, bx);
    }
    {
        cuuint64_t d[2] = {64, 16416}, s[1] = {128};
        cuuint32_t bx[2] = {64, 66};
        mWr = make_map(enc, wr, 2, d, s, bx);
        mWi = make_map(enc, wi, 2, d, s, bx);
    }
    cudaFuncSetAttribute(fused_kernel, cudaFuncAttributeMaxDynamicSharedMemorySize, SMEM_BYTES);
    fused_kernel<<<130, 384, SMEM_BYTES, cudaStreamPerThread>>>(mB, mX, mH, mCre, mCim, mX1, mWr, mWi, P);
}
```

```cpp
#include <cuda_runtime.h>
#include <cuda_bf16.h>
#include <cuda_fp16.h>
#include <cuda.h>
#include <stdint.h>

typedef __nv_bfloat16 bf16;

__device__ const __align__(128) uint32_t c_tab[5120] = {
0x3f803f80,0x3f803f80,0x3f803f80,0x3f803f80,0x3f803f80,0x3f803f80,0x3f803f80,0x3f803f80,0x3f803f80,0x3f803f80,0x3f803f80,0x3f803f80,
0x3f803f80,0x3f803f80,0x3f803f80,0x3f803f80,0x3f803f80,0x3f803f80,0x3f803f80,0x3f803f80,0x3f803f80,0x3f803f80,0x3f803f80,0x3f803f80,
0x3f803f80,0x3f803f80,0x3f803f80,0x3f803f80,0x3f803f80,0x3f803f80,0x3f803f80,0x3f803f80,0x3f223f35,0x3ef13f0e,0x3e953ec4,0x3dc93e48,
0x3f7f3f80,0x3f753f7b,0x3f623f6d,0x3f463f55,0xbf46bf35,0xbf62bf55,0xbf75bf6d,0xbf7fbf7b,0xbdc90000,0xbe95be48,0xbef1bec4,0xbf22bf0e,
0xbf22bf35,0xbef1bf0e,0xbe95bec4,0xbdc9be48,0xbf7fbf80,0xbf75bf7b,0xbf62bf6d,0xbf46bf55,0x3f463f35,0x3f623f55,0x3f753f6d,0x3f7f3f7b,
0x3dc90000,0x3e953e48,0x3ef13ec4,0x3f223f0e,0xbf7bbf80,0xbf55bf6d,0xbf0ebf35,0xbe48bec4,0x3e480000,0x3f0e3ec4,0x3f553f35,0x3f7b3f6d,
0x3f7b3f80,0x3f553f6d,0x3f0e3f35,0x3e483ec4,0xbe480000,0xbf0ebec4,0xbf55bf35,0xbf7bbf6d,0xbf7bbf80,0xbf55bf6d,0xbf0ebf35,0xbe48bec4,
0x3e480000,0x3f0e3ec4,0x3f553f35,0x3f7b3f6d,0x3f7b3f80,0x3f553f6d,0x3f0e3f35,0x3e483ec4,0xbe480000,0xbf0ebec4,0xbf55bf35,0xbf7bbf6d,
0x3ef13f35,0xbdc93e48,0xbf22bec4,0xbf75bf55,0x3e950000,0x3f463f0e,0x3f7f3f6d,0x3f623f7b,0xbf62bf35,0xbf7fbf7b,0xbf46bf6d,0xbe95bf0e,
0x3f753f80,0x3f223f55,0x3dc93ec4,0xbef1be48,0xbef1bf35,0x3dc9be48,0x3f223ec4,0x3f753f55,0xbe950000,0xbf46bf0e,0xbf7fbf6d,0xbf62bf7b,
0x3f623f35,0x3f7f3f7b,0x3f463f6d,0x3e953f0e,0xbf75bf80,0xbf22bf55,0xbdc9bec4,0x3ef13e48,0x3f6d3f80,0x3ec43f35,0xbec40000,0xbf6dbf35,
0xbf6dbf80,0xbec4bf35,0x3ec40000,0x3f6d3f35,0x3f6d3f80,0x3ec43f35,0xbec40000,0xbf6dbf35,0xbf6dbf80,0xbec4bf35,0x3ec40000,0x3f6d3f35,
0x3f6d3f80,0x3ec43f35,0xbec40000,0xbf6dbf35,0xbf6dbf80,0xbec4bf35,0x3ec40000,0x3f6d3f35,0x3f6d3f80,0x3ec43f35,0xbec40000,0xbf6dbf35,
0xbf6dbf80,0xbec4bf35,0x3ec40000,0x3f6d3f35,0x3e953f35,0xbf22be48,0xbf7fbf6d,0xbef1bf55,0xbf62bf80,0xbdc9bf0e,0x3f463ec4,0x3f753f7b,
0xbf75bf35,0xbf46bf7b,0x3dc9bec4,0x3f623f0e,0x3ef10000,0x3f7f3f55,0x3f223f6d,0xbe953e48,0xbe95bf35,0x3f223e48,0x3f7f3f6d,0x3ef13f55,
0x3f623f80,0x3dc93f0e,0xbf46bec4,0xbf75bf7b,0x3f753f35,0x3f463f7b,0xbdc93ec4,0xbf62bf0e,0xbef10000,0xbf7fbf55,0xbf22bf6d,0x3e95be48,
0xbf55bf80,0x3e48bec4,0x3f7b3f35,0x3f0e3f6d,0xbf0e0000,0xbf7bbf6d,0xbe48bf35,0x3f553ec4,0x3f553f80,0xbe483ec4,0xbf7bbf35,0xbf0ebf6d,
0x3f0e0000,0x3f7b3f6d,0x3e483f35,0xbf55bec4,0xbf55bf80,0x3e48bec4,0x3f7b3f35,0x3f0e3f6d,0xbf0e0000,0xbf7bbf6d,0xbe48bf35,0x3f553ec4,
0x3f553f80,0xbe483ec4,0xbf7bbf35,0xbf0ebf6d,0x3f0e0000,0x3f7b3f6d,0x3e483f35,0xbf55bec4,0x3dc93f35,0xbf75bf0e,0xbef1bf6d,0x3f463e48,
0xbf220000,0xbf62bf7b,0x3e95bec4,0x3f7f3f55,0xbf7fbf35,0xbe95bf55,0x3f623ec4,0x3f223f7b,0xbf46bf80,0x3ef1be48,0x3f753f6d,0xbdc93f0e,
0xbdc9bf35,0x3f753f0e,0x3ef13f6d,0xbf46be48,0x3f220000,0x3f623f7b,0xbe953ec4,0xbf7fbf55,0x3f7f3f35,0x3e953f55,0xbf62bec4,0xbf22bf7b,
0x3f463f80,0xbef13e48,0xbf75bf6d,0x3dc9bf0e,0xbf803f80,0xbf803f80,0xbf803f80,0xbf803f80,0xbf803f80,0xbf803f80,0xbf803f80,0xbf803f80,
0xbf803f80,0xbf803f80,0xbf803f80,0xbf803f80,0xbf803f80,0xbf803f80,0xbf803f80,0xbf803f80,0xbf803f80,0xbf803f80,0xbf803f80,0xbf803f80,
0xbf803f80,0xbf803f80,0xbf803f80,0xbf803f80,0xbf803f80,0xbf803f80,0xbf803f80,0xbf803f80,0xbf803f80,0xbf803f80,0xbf803f80,0xbf803f80,
0xbf46bf35,0xbf62bf55,0xbf75bf6d,0xbf7fbf7b,0xbdc98000,0xbe95be48,0xbef1bec4,0xbf22bf0e,0xbf22bf35,0xbef1bf0e,0xbe95bec4,0xbdc9be48,
0xbf7fbf80,0xbf75bf7b,0xbf62bf6d,0xbf46bf55,0x3f463f35,0x3f623f55,0x3f753f6d,0x3f7f3f7b,0x3dc98000,0x3e953e48,0x3ef13ec4,0x3f223f0e,
0x3f223f35,0x3ef13f0e,0x3e953ec4,0x3dc93e48,0x3f7f3f80,0x3f753f7b,0x3f623f6d,0x3f463f55,0x3e488000,0x3f0e3ec4,0x3f553f35,0x3f7b3f6d,
0x3f7b3f80,0x3f553f6d,0x3f0e3f35,0x3e483ec4,0xbe488000,0xbf0ebec4,0xbf55bf35,0xbf7bbf6d,0xbf7bbf80,0xbf55bf6d,0xbf0ebf35,0xbe48bec4,
0x3e488000,0x3f0e3ec4,0x3f553f35,0x3f7b3f6d,0x3f7b3f80,0x3f553f6d,0x3f0e3f35,0x3e483ec4,0xbe488000,0xbf0ebec4,0xbf55bf35,0xbf7bbf6d,
0xbf7bbf80,0xbf55bf6d,0xbf0ebf35,0xbe48bec4,0xbf62bf35,0xbf7fbf7b,0xbf46bf6d,0xbe95bf0e,0x3f753f80,0x3f223f55,0x3dc93ec4,0xbef1be48,
0xbef1bf35,0x3dc9be48,0x3f223ec4,0x3f753f55,0xbe958000,0xbf46bf0e,0xbf7fbf6d,0xbf62bf7b,0x3f623f35,0x3f7f3f7b,0x3f463f6d,0x3e953f0e,
0xbf75bf80,0xbf22bf55,0xbdc9bec4,0x3ef13e48,0x3ef13f35,0xbdc93e48,0xbf22bec4,0xbf75bf55,0x3e958000,0x3f463f0e,0x3f7f3f6d,0x3f623f7b,
0xbec48000,0xbf6dbf35,0xbf6dbf80,0xbec4bf35,0x3ec48000,0x3f6d3f35,0x3f6d3f80,0x3ec43f35,0xbec48000,0xbf6dbf35,0xbf6dbf80,0xbec4bf35,
0x3ec48000,0x3f6d3f35,0x3f6d3f80,0x3ec43f35,0xbec48000,0xbf6dbf35,0xbf6dbf80,0xbec4bf35,0x3ec48000,0x3f6d3f35,0x3f6d3f80,0x3ec43f35,
0xbec48000,0xbf6dbf35,0xbf6dbf80,0xbec4bf35,0x3ec48000,0x3f6d3f35,0x3f6d3f80,0x3ec43f35,0xbf75bf35,0xbf46bf7b,0x3dc9bec4,0x3f623f0e,
0x3ef18000,0x3f7f3f55,0x3f223f6d,0xbe953e48,0xbe95bf35,0x3f223e48,0x3f7f3f6d,0x3ef13f55,0x3f623f80,0x3dc93f0e,0xbf46bec4,0xbf75bf7b,
0x3f753f35,0x3f463f7b,0xbdc93ec4,0xbf62bf0e,0xbef18000,0xbf7fbf55,0xbf22bf6d,0x3e95be48,0x3e953f35,0xbf22be48,0xbf7fbf6d,0xbef1bf55,
0xbf62bf80,0xbdc9bf0e,0x3f463ec4,0x3f753f7b,0x3f0e8000,0x3f7b3f6d,0x3e483f35,0xbf55bec4,0xbf55bf80,0x3e48bec4,0x3f7b3f35,0x3f0e3f6d,
0xbf0e8000,0xbf7bbf6d,0xbe48bf35,0x3f553ec4,0x3f553f80,0xbe483ec4,0xbf7bbf35,0xbf0ebf6d,0x3f0e8000,0x3f7b3f6d,0x3e483f35,0xbf55bec4,
0xbf55bf80,0x3e48bec4,0x3f7b3f35,0x3f0e3f6d,0xbf0e8000,0xbf7bbf6d,0xbe48bf35,0x3f553ec4,0x3f553f80,0xbe483ec4,0xbf7bbf35,0xbf0ebf6d,
0xbf7fbf35,0xbe95bf55,0x3f623ec4,0x3f223f7b,0xbf46bf80,0x3ef1be48,0x3f753f6d,0xbdc93f0e,0xbdc9bf35,0x3f753f0e,0x3ef13f6d,0xbf46be48,
0x3f228000,0x3f623f7b,0xbe953ec4,0xbf7fbf55,0x3f7f3f35,0x3e953f55,0xbf62bec4,0xbf22bf7b,0x3f463f80,0xbef13e48,0xbf75bf6d,0x3dc9bf0e,
0x3dc93f35,0xbf75bf0e,0xbef1bf6d,0x3f463e48,0xbf228000,0xbf62bf7b,0x3e95bec4,0x3f7f3f55,0x3f353f80,0xbf350000,0xbf35bf80,0x3f350000,
0x3f353f80,0xbf350000,0xbf35bf80,0x3f350000,0x3f353f80,0xbf350000,0xbf35bf80,0x3f350000,0x3f353f80,0xbf350000,0xbf35bf80,0x3f350000,
0x3f353f80,0xbf350000,0xbf35bf80,0x3f350000,0x3f353f80,0xbf350000,0xbf35bf80,0x3f350000,0x3f353f80,0xbf350000,0xbf35bf80,0x3f350000,
0x3f353f80,0xbf350000,0xbf35bf80,0x3f350000,0xbdc93f35,0xbf75bf55,0x3ef1bec4,0x3f463f7b,0x3f223f80,0xbf62be48,0xbe95bf6d,0x3f7f3f0e,
0xbf7fbf35,0x3e95bf0e,0x3f623f6d,0xbf223e48,0xbf460000,0xbef1bf7b,0x3f753ec4,0x3dc93f55,0x3dc9bf35,0x3f753f55,0xbef13ec4,0xbf46bf7b,
0xbf22bf80,0x3f623e48,0x3e953f6d,0xbf7fbf0e,0x3f7f3f35,0xbe953f0e,0xbf62bf6d,0x3f22be48,0x3f460000,0x3ef13f7b,0xbf75bec4,0xbdc9bf55,
0xbf0ebf80,0x3f7b3ec4,0xbe483f35,0xbf55bf6d,0x3f550000,0x3e483f6d,0xbf7bbf35,0x3f0ebec4,0x3f0e3f80,0xbf7bbec4,0x3e48bf35,0x3f553f6d,
0xbf550000,0xbe48bf6d,0x3f7b3f35,0xbf0e3ec4,0xbf0ebf80,0x3f7b3ec4,0xbe483f35,0xbf55bf6d,0x3f550000,0x3e483f6d,0xbf7bbf35,0x3f0ebec4,
0x3f0e3f80,0xbf7bbec4,0x3e48bf35,0x3f553f6d,0xbf550000,0xbe48bf6d,0x3f7b3f35,0xbf0e3ec4,0xbe953f35,0xbf22bf7b,0x3f7f3ec4,0xbef13f0e,
0x3f620000,0xbdc93f55,0xbf46bf6d,0x3f753e48,0xbf75bf35,0x3f46be48,0x3dc93f6d,0xbf62bf55,0x3ef13f80,0xbf7fbf0e,0x3f22bec4,0x3e953f7b,
0x3e95bf35,0x3f223f7b,0xbf7fbec4,0x3ef1bf0e,0xbf620000,0x3dc9bf55,0x3f463f6d,0xbf75be48,0x3f753f35,0xbf463e48,0xbdc9bf6d,0x3f623f55,
0xbef1bf80,0x3f7f3f0e,0xbf223ec4,0xbe95bf7b,0x3ec43f80,0xbf6dbf35,0x3f6d0000,0xbec43f35,0xbec4bf80,0x3f6d3f35,0xbf6d0000,0x3ec4bf35,
0x3ec43f80,0xbf6dbf35,0x3f6d0000,0xbec43f35,0xbec4bf80,0x3f6d3f35,0xbf6d0000,0x3ec4bf35,0x3ec43f80,0xbf6dbf35,0x3f6d0000,0xbec43f35,
0xbec4bf80,0x3f6d3f35,0xbf6d0000,0x3ec4bf35,0x3ec43f80,0xbf6dbf35,0x3f6d0000,0xbec43f35,0xbec4bf80,0x3f6d3f35,0xbf6d0000,0x3ec4bf35,
0xbef13f35,0xbdc9bf7b,0x3f223f6d,0xbf75bf0e,0xbe95bf80,0x3f463f55,0xbf7fbec4,0x3f62be48,0xbf62bf35,0x3f7f3e48,0xbf463ec4,0x3e95bf55,
0x3f750000,0xbf223f0e,0x3dc9bf6d,0x3ef13f7b,0x3ef1bf35,0x3dc93f7b,0xbf22bf6d,0x3f753f0e,0x3e953f80,0xbf46bf55,0x3f7f3ec4,0xbf623e48,
0x3f623f35,0xbf7fbe48,0x3f46bec4,0xbe953f55,0xbf750000,0x3f22bf0e,0xbdc93f6d,0xbef1bf7b,0xbe48bf80,0x3f0e3f6d,0xbf55bf35,0x3f7b3ec4,
0xbf7b0000,0x3f55bec4,0xbf0e3f35,0x3e48bf6d,0x3e483f80,0xbf0ebf6d,0x3f553f35,0xbf7bbec4,0x3f7b0000,0xbf553ec4,0x3f0ebf35,0xbe483f6d,
0xbe48bf80,0x3f0e3f6d,0xbf55bf35,0x3f7b3ec4,0xbf7b0000,0x3f55bec4,0xbf0e3f35,0x3e48bf6d,0x3e483f80,0xbf0ebf6d,0x3f553f35,0xbf7bbec4,
0x3f7b0000,0xbf553ec4,0x3f0ebf35,0xbe483f6d,0xbf223f35,0x3ef1bf55,0xbe953f6d,0x3dc9bf7b,0xbf7f0000,0x3f75be48,0xbf623ec4,0x3f46bf0e,
0xbf46bf35,0x3f623f0e,0xbf75bec4,0x3f7f3e48,0xbdc9bf80,0x3e953f7b,0xbef1bf6d,0x3f223f55,0x3f22bf35,0xbef13f55,0x3e95bf6d,0xbdc93f7b,
0x3f7f0000,0xbf753e48,0x3f62bec4,0xbf463f0e,0x3f463f35,0xbf62bf0e,0x3f753ec4,0xbf7fbe48,0x3dc93f80,0xbe95bf7b,0x3ef13f6d,0xbf22bf55,
0xbf358000,0xbf35bf80,0x3f358000,0x3f353f80,0xbf358000,0xbf35bf80,0x3f358000,0x3f353f80,0xbf358000,0xbf35bf80,0x3f358000,0x3f353f80,
0xbf358000,0xbf35bf80,0x3f358000,0x3f353f80,0xbf358000,0xbf35bf80,0x3f358000,0x3f353f80,0xbf358000,0xbf35bf80,0x3f358000,0x3f353f80,
0xbf358000,0xbf35bf80,0x3f358000,0x3f353f80,0xbf358000,0xbf35bf80,0x3f358000,0x3f353f80,0xbf7fbf35,0x3e95bf0e,0x3f623f6d,0xbf223e48,
0xbf468000,0xbef1bf7b,0x3f753ec4,0x3dc93f55,0x3dc9bf35,0x3f753f55,0xbef13ec4,0xbf46bf7b,0xbf22bf80,0x3f623e48,0x3e953f6d,0xbf7fbf0e,
0x3f7f3f35,0xbe953f0e,0xbf62bf6d,0x3f22be48,0x3f468000,0x3ef13f7b,0xbf75bec4,0xbdc9bf55,0xbdc93f35,0xbf75bf55,0x3ef1bec4,0x3f463f7b,
0x3f223f80,0xbf62be48,0xbe95bf6d,0x3f7f3f0e,0x3f558000,0x3e483f6d,0xbf7bbf35,0x3f0ebec4,0x3f0e3f80,0xbf7bbec4,0x3e48bf35,0x3f553f6d,
0xbf558000,0xbe48bf6d,0x3f7b3f35,0xbf0e3ec4,0xbf0ebf80,0x3f7b3ec4,0xbe483f35,0xbf55bf6d,0x3f558000,0x3e483f6d,0xbf7bbf35,0x3f0ebec4,
0x3f0e3f80,0xbf7bbec4,0x3e48bf35,0x3f553f6d,0xbf558000,0xbe48bf6d,0x3f7b3f35,0xbf0e3ec4,0xbf0ebf80,0x3f7b3ec4,0xbe483f35,0xbf55bf6d,
0xbf75bf35,0x3f46be48,0x3dc93f6d,0xbf62bf55,0x3ef13f80,0xbf7fbf0e,0x3f22bec4,0x3e953f7b,0x3e95bf35,0x3f223f7b,0xbf7fbec4,0x3ef1bf0e,
0xbf628000,0x3dc9bf55,0x3f463f6d,0xbf75be48,0x3f753f35,0xbf463e48,0xbdc9bf6d,0x3f623f55,0xbef1bf80,0x3f7f3f0e,0xbf223ec4,0xbe95bf7b,
0xbe953f35,0xbf22bf7b,0x3f7f3ec4,0xbef13f0e,0x3f628000,0xbdc93f55,0xbf46bf6d,0x3f753e48,0xbf6d8000,0x3ec4bf35,0x3ec43f80,0xbf6dbf35,
0x3f6d8000,0xbec43f35,0xbec4bf80,0x3f6d3f35,0xbf6d8000,0x3ec4bf35,0x3ec43f80,0xbf6dbf35,0x3f6d8000,0xbec43f35,0xbec4bf80,0x3f6d3f35,
0xbf6d8000,0x3ec4bf35,0x3ec43f80,0xbf6dbf35,0x3f6d8000,0xbec43f35,0xbec4bf80,0x3f6d3f35,0xbf6d8000,0x3ec4bf35,0x3ec43f80,0xbf6dbf35,
0x3f6d8000,0xbec43f35,0xbec4bf80,0x3f6d3f35,0xbf62bf35,0x3f7f3e48,0xbf463ec4,0x3e95bf55,0x3f758000,0xbf223f0e,0x3dc9bf6d,0x3ef13f7b,
0x3ef1bf35,0x3dc93f7b,0xbf22bf6d,0x3f753f0e,0x3e953f80,0xbf46bf55,0x3f7f3ec4,0xbf623e48,0x3f623f35,0xbf7fbe48,0x3f46bec4,0xbe953f55,
0xbf758000,0x3f22bf0e,0xbdc93f6d,0xbef1bf7b,0xbef13f35,0xbdc9bf7b,0x3f223f6d,0xbf75bf0e,0xbe95bf80,0x3f463f55,0xbf7fbec4,0x3f62be48,
0x3f7b8000,0xbf553ec4,0x3f0ebf35,0xbe483f6d,0xbe48bf80,0x3f0e3f6d,0xbf55bf35,0x3f7b3ec4,0xbf7b8000,0x3f55bec4,0xbf0e3f35,0x3e48bf6d,
0x3e483f80,0xbf0ebf6d,0x3f553f35,0xbf7bbec4,0x3f7b8000,0xbf553ec4,0x3f0ebf35,0xbe483f6d,0xbe48bf80,0x3f0e3f6d,0xbf55bf35,0x3f7b3ec4,
0xbf7b8000,0x3f55bec4,0xbf0e3f35,0x3e48bf6d,0x3e483f80,0xbf0ebf6d,0x3f553f35,0xbf7bbec4,0xbf46bf35,0x3f623f0e,0xbf75bec4,0x3f7f3e48,
0xbdc9bf80,0x3e953f7b,0xbef1bf6d,0x3f223f55,0x3f22bf35,0xbef13f55,0x3e95bf6d,0xbdc93f7b,0x3f7f8000,0xbf753e48,0x3f62bec4,0xbf463f0e,
0x3f463f35,0xbf62bf0e,0x3f753ec4,0xbf7fbe48,0x3dc93f80,0xbe95bf7b,0x3ef13f6d,0xbf22bf55,0xbf223f35,0x3ef1bf55,0xbe953f6d,0x3dc9bf7b,
0xbf7f8000,0x3f75be48,0xbf623ec4,0x3f46bf0e,0x3f80,0xbf80,0x3f80,0xbf80,0x3f80,0xbf80,0x3f80,0xbf80,
0x3f80,0xbf80,0x3f80,0xbf80,0x3f80,0xbf80,0x3f80,0xbf80,0x3f80,0xbf80,0x3f80,0xbf80,
0x3f80,0xbf80,0x3f80,0xbf80,0x3f80,0xbf80,0x3f80,0xbf80,0x3f80,0xbf80,0x3f80,0xbf80,
0xbf463f35,0x3f62bf0e,0xbf753ec4,0x3f7fbe48,0xbdc93f80,0x3e95bf7b,0xbef13f6d,0x3f22bf55,0xbf22bf35,0x3ef13f55,0xbe95bf6d,0x3dc93f7b,
0xbf7f0000,0x3f753e48,0xbf62bec4,0x3f463f0e,0x3f46bf35,0xbf623f0e,0x3f75bec4,0xbf7f3e48,0x3dc9bf80,0xbe953f7b,0x3ef1bf6d,0xbf223f55,
0x3f223f35,0xbef1bf55,0x3e953f6d,0xbdc9bf7b,0x3f7f0000,0xbf75be48,0x3f623ec4,0xbf46bf0e,0x3e48bf80,0xbf0e3f6d,0x3f55bf35,0xbf7b3ec4,
0x3f7b0000,0xbf55bec4,0x3f0e3f35,0xbe48bf6d,0xbe483f80,0x3f0ebf6d,0xbf553f35,0x3f7bbec4,0xbf7b0000,0x3f553ec4,0xbf0ebf35,0x3e483f6d,
0x3e48bf80,0xbf0e3f6d,0x3f55bf35,0xbf7b3ec4,0x3f7b0000,0xbf55bec4,0x3f0e3f35,0xbe48bf6d,0xbe483f80,0x3f0ebf6d,0xbf553f35,0x3f7bbec4,
0xbf7b0000,0x3f553ec4,0xbf0ebf35,0x3e483f6d,0xbf623f35,0x3f7fbe48,0xbf46bec4,0x3e953f55,0x3f750000,0xbf22bf0e,0x3dc93f6d,0x3ef1bf7b,
0xbef1bf35,0xbdc93f7b,0x3f22bf6d,0xbf753f0e,0xbe953f80,0x3f46bf55,0xbf7f3ec4,0x3f623e48,0x3f62bf35,0xbf7f3e48,0x3f463ec4,0xbe95bf55,
0xbf750000,0x3f223f0e,0xbdc9bf6d,0xbef13f7b,0x3ef13f35,0x3dc9bf7b,0xbf223f6d,0x3f75bf0e,0x3e95bf80,0xbf463f55,0x3f7fbec4,0xbf62be48,
0xbec43f80,0x3f6dbf35,0xbf6d0000,0x3ec43f35,0x3ec4bf80,0xbf6d3f35,0x3f6d0000,0xbec4bf35,0xbec43f80,0x3f6dbf35,0xbf6d0000,0x3ec43f35,
0x3ec4bf80,0xbf6d3f35,0x3f6d0000,0xbec4bf35,0xbec43f80,0x3f6dbf35,0xbf6d0000,0x3ec43f35,0x3ec4bf80,0xbf6d3f35,0x3f6d0000,0xbec4bf35,
0xbec43f80,0x3f6dbf35,0xbf6d0000,0x3ec43f35,0x3ec4bf80,0xbf6d3f35,0x3f6d0000,0xbec4bf35,0xbf753f35,0x3f463e48,0x3dc9bf6d,0xbf623f55,
0x3ef1bf80,0xbf7f3f0e,0x3f223ec4,0x3e95bf7b,0xbe95bf35,0xbf223f7b,0x3f7fbec4,0xbef1bf0e,0x3f620000,0xbdc9bf55,0xbf463f6d,0x3f75be48,
0x3f75bf35,0xbf46be48,0xbdc93f6d,0x3f62bf55,0xbef13f80,0x3f7fbf0e,0xbf22bec4,0xbe953f7b,0x3e953f35,0x3f22bf7b,0xbf7f3ec4,0x3ef13f0e,
0xbf620000,0x3dc93f55,0x3f46bf6d,0xbf753e48,0x3f0ebf80,0xbf7b3ec4,0x3e483f35,0x3f55bf6d,0xbf550000,0xbe483f6d,0x3f7bbf35,0xbf0ebec4,
0xbf0e3f80,0x3f7bbec4,0xbe48bf35,0xbf553f6d,0x3f550000,0x3e48bf6d,0xbf7b3f35,0x3f0e3ec4,0x3f0ebf80,0xbf7b3ec4,0x3e483f35,0x3f55bf6d,
0xbf550000,0xbe483f6d,0x3f7bbf35,0xbf0ebec4,0xbf0e3f80,0x3f7bbec4,0xbe48bf35,0xbf553f6d,0x3f550000,0x3e48bf6d,0xbf7b3f35,0x3f0e3ec4,
0xbf7f3f35,0x3e953f0e,0x3f62bf6d,0xbf22be48,0xbf460000,0xbef13f7b,0x3f75bec4,0x3dc9bf55,0xbdc9bf35,0xbf753f55,0x3ef13ec4,0x3f46bf7b,
0x3f22bf80,0xbf623e48,0xbe953f6d,0x3f7fbf0e,0x3f7fbf35,0xbe95bf0e,0xbf623f6d,0x3f223e48,0x3f460000,0x3ef1bf7b,0xbf753ec4,0xbdc93f55,
0x3dc93f35,0x3f75bf55,0xbef1bec4,0xbf463f7b,0xbf223f80,0x3f62be48,0x3e95bf6d,0xbf7f3f0e,0xbf808000,0x3f808000,0xbf808000,0x3f808000,
0xbf808000,0x3f808000,0xbf808000,0x3f808000,0xbf808000,0x3f808000,0xbf808000,0x3f808000,0xbf808000,0x3f808000,0xbf808000,0x3f808000,
0xbf808000,0x3f808000,0xbf808000,0x3f808000,0xbf808000,0x3f808000,0xbf808000,0x3f808000,0xbf808000,0x3f808000,0xbf808000,0x3f808000,
0xbf808000,0x3f808000,0xbf808000,0x3f808000,0xbf22bf35,0x3ef13f55,0xbe95bf6d,0x3dc93f7b,0xbf7f8000,0x3f753e48,0xbf62bec4,0x3f463f0e,
0x3f46bf35,0xbf623f0e,0x3f75bec4,0xbf7f3e48,0x3dc9bf80,0xbe953f7b,0x3ef1bf6d,0xbf223f55,0x3f223f35,0xbef1bf55,0x3e953f6d,0xbdc9bf7b,
0x3f7f8000,0xbf75be48,0x3f623ec4,0xbf46bf0e,0xbf463f35,0x3f62bf0e,0xbf753ec4,0x3f7fbe48,0xbdc93f80,0x3e95bf7b,0xbef13f6d,0x3f22bf55,
0x3f7b8000,0xbf55bec4,0x3f0e3f35,0xbe48bf6d,0xbe483f80,0x3f0ebf6d,0xbf553f35,0x3f7bbec4,0xbf7b8000,0x3f553ec4,0xbf0ebf35,0x3e483f6d,
0x3e48bf80,0xbf0e3f6d,0x3f55bf35,0xbf7b3ec4,0x3f7b8000,0xbf55bec4,0x3f0e3f35,0xbe48bf6d,0xbe483f80,0x3f0ebf6d,0xbf553f35,0x3f7bbec4,
0xbf7b8000,0x3f553ec4,0xbf0ebf35,0x3e483f6d,0x3e48bf80,0xbf0e3f6d,0x3f55bf35,0xbf7b3ec4,0xbef1bf35,0xbdc93f7b,0x3f22bf6d,0xbf753f0e,
0xbe953f80,0x3f46bf55,0xbf7f3ec4,0x3f623e48,0x3f62bf35,0xbf7f3e48,0x3f463ec4,0xbe95bf55,0xbf758000,0x3f223f0e,0xbdc9bf6d,0xbef13f7b,
0x3ef13f35,0x3dc9bf7b,0xbf223f6d,0x3f75bf0e,0x3e95bf80,0xbf463f55,0x3f7fbec4,0xbf62be48,0xbf623f35,0x3f7fbe48,0xbf46bec4,0x3e953f55,
0x3f758000,0xbf22bf0e,0x3dc93f6d,0x3ef1bf7b,0xbf6d8000,0x3ec43f35,0x3ec4bf80,0xbf6d3f35,0x3f6d8000,0xbec4bf35,0xbec43f80,0x3f6dbf35,
0xbf6d8000,0x3ec43f35,0x3ec4bf80,0xbf6d3f35,0x3f6d8000,0xbec4bf35,0xbec43f80,0x3f6dbf35,0xbf6d8000,0x3ec43f35,0x3ec4bf80,0xbf6d3f35,
0x3f6d8000,0xbec4bf35,0xbec43f80,0x3f6dbf35,0xbf6d8000,0x3ec43f35,0x3ec4bf80,0xbf6d3f35,0x3f6d8000,0xbec4bf35,0xbec43f80,0x3f6dbf35,
0xbe95bf35,0xbf223f7b,0x3f7fbec4,0xbef1bf0e,0x3f628000,0xbdc9bf55,0xbf463f6d,0x3f75be48,0x3f75bf35,0xbf46be48,0xbdc93f6d,0x3f62bf55,
0xbef13f80,0x3f7fbf0e,0xbf22bec4,0xbe953f7b,0x3e953f35,0x3f22bf7b,0xbf7f3ec4,0x3ef13f0e,0xbf628000,0x3dc93f55,0x3f46bf6d,0xbf753e48,
0xbf753f35,0x3f463e48,0x3dc9bf6d,0xbf623f55,0x3ef1bf80,0xbf7f3f0e,0x3f223ec4,0x3e95bf7b,0x3f558000,0x3e48bf6d,0xbf7b3f35,0x3f0e3ec4,
0x3f0ebf80,0xbf7b3ec4,0x3e483f35,0x3f55bf6d,0xbf558000,0xbe483f6d,0x3f7bbf35,0xbf0ebec4,0xbf0e3f80,0x3f7bbec4,0xbe48bf35,0xbf553f6d,
0x3f558000,0x3e48bf6d,0xbf7b3f35,0x3f0e3ec4,0x3f0ebf80,0xbf7b3ec4,0x3e483f35,0x3f55bf6d,0xbf558000,0xbe483f6d,0x3f7bbf35,0xbf0ebec4,
0xbf0e3f80,0x3f7bbec4,0xbe48bf35,0xbf553f6d,0xbdc9bf35,0xbf753f55,0x3ef13ec4,0x3f46bf7b,0x3f22bf80,0xbf623e48,0xbe953f6d,0x3f7fbf0e,
0x3f7fbf35,0xbe95bf0e,0xbf623f6d,0x3f223e48,0x3f468000,0x3ef1bf7b,0xbf753ec4,0xbdc93f55,0x3dc93f35,0x3f75bf55,0xbef1bec4,0xbf463f7b,
0xbf223f80,0x3f62be48,0x3e95bf6d,0xbf7f3f0e,0xbf7f3f35,0x3e953f0e,0x3f62bf6d,0xbf22be48,0xbf468000,0xbef13f7b,0x3f75bec4,0x3dc9bf55,
0xbf353f80,0x3f350000,0x3f35bf80,0xbf350000,0xbf353f80,0x3f350000,0x3f35bf80,0xbf350000,0xbf353f80,0x3f350000,0x3f35bf80,0xbf350000,
0xbf353f80,0x3f350000,0x3f35bf80,0xbf350000,0xbf353f80,0x3f350000,0x3f35bf80,0xbf350000,0xbf353f80,0x3f350000,0x3f35bf80,0xbf350000,
0xbf353f80,0x3f350000,0x3f35bf80,0xbf350000,0xbf353f80,0x3f350000,0x3f35bf80,0xbf350000,0xbf7f3f35,0xbe953f55,0x3f62bec4,0x3f22bf7b,
0xbf463f80,0x3ef13e48,0x3f75bf6d,0xbdc9bf0e,0x3dc9bf35,0xbf753f0e,0xbef13f6d,0x3f46be48,0xbf220000,0xbf623f7b,0x3e953ec4,0x3f7fbf55,
0x3f7fbf35,0x3e95bf55,0xbf623ec4,0xbf223f7b,0x3f46bf80,0xbef1be48,0xbf753f6d,0x3dc93f0e,0xbdc93f35,0x3f75bf0e,0x3ef1bf6d,0xbf463e48,
0x3f220000,0x3f62bf7b,0xbe95bec4,0xbf7f3f55,0x3f55bf80,0xbe48bec4,0xbf7b3f35,0xbf0e3f6d,0x3f0e0000,0x3f7bbf6d,0x3e48bf35,0xbf553ec4,
0xbf553f80,0x3e483ec4,0x3f7bbf35,0x3f0ebf6d,0xbf0e0000,0xbf7b3f6d,0xbe483f35,0x3f55bec4,0x3f55bf80,0xbe48bec4,0xbf7b3f35,0xbf0e3f6d,
0x3f0e0000,0x3f7bbf6d,0x3e48bf35,0xbf553ec4,0xbf553f80,0x3e483ec4,0x3f7bbf35,0x3f0ebf6d,0xbf0e0000,0xbf7b3f6d,0xbe483f35,0x3f55bec4,
0xbf753f35,0xbf463f7b,0x3dc93ec4,0x3f62bf0e,0x3ef10000,0x3f7fbf55,0x3f22bf6d,0xbe95be48,0x3e95bf35,0xbf223e48,0xbf7f3f6d,0xbef13f55,
0xbf623f80,0xbdc93f0e,0x3f46bec4,0x3f75bf7b,0x3f75bf35,0x3f46bf7b,0xbdc9bec4,0xbf623f0e,0xbef10000,0xbf7f3f55,0xbf223f6d,0x3e953e48,
0xbe953f35,0x3f22be48,0x3f7fbf6d,0x3ef1bf55,0x3f62bf80,0x3dc9bf0e,0xbf463ec4,0xbf753f7b,0xbf6d3f80,0xbec43f35,0x3ec40000,0x3f6dbf35,
0x3f6dbf80,0x3ec4bf35,0xbec40000,0xbf6d3f35,0xbf6d3f80,0xbec43f35,0x3ec40000,0x3f6dbf35,0x3f6dbf80,0x3ec4bf35,0xbec40000,0xbf6d3f35,
0xbf6d3f80,0xbec43f35,0x3ec40000,0x3f6dbf35,0x3f6dbf80,0x3ec4bf35,0xbec40000,0xbf6d3f35,0xbf6d3f80,0xbec43f35,0x3ec40000,0x3f6dbf35,
0x3f6dbf80,0x3ec4bf35,0xbec40000,0xbf6d3f35,0xbf623f35,0xbf7f3f7b,0xbf463f6d,0xbe953f0e,0x3f75bf80,0x3f22bf55,0x3dc9bec4,0xbef13e48,
0x3ef1bf35,0xbdc9be48,0xbf223ec4,0xbf753f55,0x3e950000,0x3f46bf0e,0x3f7fbf6d,0x3f62bf7b,0x3f62bf35,0x3f7fbf7b,0x3f46bf6d,0x3e95bf0e,
0xbf753f80,0xbf223f55,0xbdc93ec4,0x3ef1be48,0xbef13f35,0x3dc93e48,0x3f22bec4,0x3f75bf55,0xbe950000,0xbf463f0e,0xbf7f3f6d,0xbf623f7b,
0x3f7bbf80,0x3f55bf6d,0x3f0ebf35,0x3e48bec4,0xbe480000,0xbf0e3ec4,0xbf553f35,0xbf7b3f6d,0xbf7b3f80,0xbf553f6d,0xbf0e3f35,0xbe483ec4,
0x3e480000,0x3f0ebec4,0x3f55bf35,0x3f7bbf6d,0x3f7bbf80,0x3f55bf6d,0x3f0ebf35,0x3e48bec4,0xbe480000,0xbf0e3ec4,0xbf553f35,0xbf7b3f6d,
0xbf7b3f80,0xbf553f6d,0xbf0e3f35,0xbe483ec4,0x3e480000,0x3f0ebec4,0x3f55bf35,0x3f7bbf6d,0xbf463f35,0xbf623f55,0xbf753f6d,0xbf7f3f7b,
0xbdc90000,0xbe953e48,0xbef13ec4,0xbf223f0e,0x3f22bf35,0x3ef1bf0e,0x3e95bec4,0x3dc9be48,0x3f7fbf80,0x3f75bf7b,0x3f62bf6d,0x3f46bf55,
0x3f46bf35,0x3f62bf55,0x3f75bf6d,0x3f7fbf7b,0x3dc90000,0x3e95be48,0x3ef1bec4,0x3f22bf0e,0xbf223f35,0xbef13f0e,0xbe953ec4,0xbdc93e48,
0xbf7f3f80,0xbf753f7b,0xbf623f6d,0xbf463f55,0xbf358000,0xbf353f80,0x3f358000,0x3f35bf80,0xbf358000,0xbf353f80,0x3f358000,0x3f35bf80,
0xbf358000,0xbf353f80,0x3f358000,0x3f35bf80,0xbf358000,0xbf353f80,0x3f358000,0x3f35bf80,0xbf358000,0xbf353f80,0x3f358000,0x3f35bf80,
0xbf358000,0xbf353f80,0x3f358000,0x3f35bf80,0xbf358000,0xbf353f80,0x3f358000,0x3f35bf80,0xbf358000,0xbf353f80,0x3f358000,0x3f35bf80,
0x3dc9bf35,0xbf753f0e,0xbef13f6d,0x3f46be48,0xbf228000,0xbf623f7b,0x3e953ec4,0x3f7fbf55,0x3f7fbf35,0x3e95bf55,0xbf623ec4,0xbf223f7b,
0x3f46bf80,0xbef1be48,0xbf753f6d,0x3dc93f0e,0xbdc93f35,0x3f75bf0e,0x3ef1bf6d,0xbf463e48,0x3f228000,0x3f62bf7b,0xbe95bec4,0xbf7f3f55,
0xbf7f3f35,0xbe953f55,0x3f62bec4,0x3f22bf7b,0xbf463f80,0x3ef13e48,0x3f75bf6d,0xbdc9bf0e,0x3f0e8000,0x3f7bbf6d,0x3e48bf35,0xbf553ec4,
0xbf553f80,0x3e483ec4,0x3f7bbf35,0x3f0ebf6d,0xbf0e8000,0xbf7b3f6d,0xbe483f35,0x3f55bec4,0x3f55bf80,0xbe48bec4,0xbf7b3f35,0xbf0e3f6d,
0x3f0e8000,0x3f7bbf6d,0x3e48bf35,0xbf553ec4,0xbf553f80,0x3e483ec4,0x3f7bbf35,0x3f0ebf6d,0xbf0e8000,0xbf7b3f6d,0xbe483f35,0x3f55bec4,
0x3f55bf80,0xbe48bec4,0xbf7b3f35,0xbf0e3f6d,0x3e95bf35,0xbf223e48,0xbf7f3f6d,0xbef13f55,0xbf623f80,0xbdc93f0e,0x3f46bec4,0x3f75bf7b,
0x3f75bf35,0x3f46bf7b,0xbdc9bec4,0xbf623f0e,0xbef18000,0xbf7f3f55,0xbf223f6d,0x3e953e48,0xbe953f35,0x3f22be48,0x3f7fbf6d,0x3ef1bf55,
0x3f62bf80,0x3dc9bf0e,0xbf463ec4,0xbf753f7b,0xbf753f35,0xbf463f7b,0x3dc93ec4,0x3f62bf0e,0x3ef18000,0x3f7fbf55,0x3f22bf6d,0xbe95be48,
0xbec48000,0xbf6d3f35,0xbf6d3f80,0xbec43f35,0x3ec48000,0x3f6dbf35,0x3f6dbf80,0x3ec4bf35,0xbec48000,0xbf6d3f35,0xbf6d3f80,0xbec43f35,
0x3ec48000,0x3f6dbf35,0x3f6dbf80,0x3ec4bf35,0xbec48000,0xbf6d3f35,0xbf6d3f80,0xbec43f35,0x3ec48000,0x3f6dbf35,0x3f6dbf80,0x3ec4bf35,
0xbec48000,0xbf6d3f35,0xbf6d3f80,0xbec43f35,0x3ec48000,0x3f6dbf35,0x3f6dbf80,0x3ec4bf35,0x3ef1bf35,0xbdc9be48,0xbf223ec4,0xbf753f55,
0x3e958000,0x3f46bf0e,0x3f7fbf6d,0x3f62bf7b,0x3f62bf35,0x3f7fbf7b,0x3f46bf6d,0x3e95bf0e,0xbf753f80,0xbf223f55,0xbdc93ec4,0x3ef1be48,
0xbef13f35,0x3dc93e48,0x3f22bec4,0x3f75bf55,0xbe958000,0xbf463f0e,0xbf7f3f6d,0xbf623f7b,0xbf623f35,0xbf7f3f7b,0xbf463f6d,0xbe953f0e,
0x3f75bf80,0x3f22bf55,0x3dc9bec4,0xbef13e48,0x3e488000,0x3f0ebec4,0x3f55bf35,0x3f7bbf6d,0x3f7bbf80,0x3f55bf6d,0x3f0ebf35,0x3e48bec4,
0xbe488000,0xbf0e3ec4,0xbf553f35,0xbf7b3f6d,0xbf7b3f80,0xbf553f6d,0xbf0e3f35,0xbe483ec4,0x3e488000,0x3f0ebec4,0x3f55bf35,0x3f7bbf6d,
0x3f7bbf80,0x3f55bf6d,0x3f0ebf35,0x3e48bec4,0xbe488000,0xbf0e3ec4,0xbf553f35,0xbf7b3f6d,0xbf7b3f80,0xbf553f6d,0xbf0e3f35,0xbe483ec4,
0x3f22bf35,0x3ef1bf0e,0x3e95bec4,0x3dc9be48,0x3f7fbf80,0x3f75bf7b,0x3f62bf6d,0x3f46bf55,0x3f46bf35,0x3f62bf55,0x3f75bf6d,0x3f7fbf7b,
0x3dc98000,0x3e95be48,0x3ef1bec4,0x3f22bf0e,0xbf223f35,0xbef13f0e,0xbe953ec4,0xbdc93e48,0xbf7f3f80,0xbf753f7b,0xbf623f6d,0xbf463f55,
0xbf463f35,0xbf623f55,0xbf753f6d,0xbf7f3f7b,0xbdc98000,0xbe953e48,0xbef13ec4,0xbf223f0e,0x3f803f80,0x3f803f80,0x3f803f80,0x3f803f80,
0x3f803f80,0x3f803f80,0x3f803f80,0x3f803f80,0x3f803f80,0x3f803f80,0x3f803f80,0x3f803f80,0x3f803f80,0x3f803f80,0x3f803f80,0x3f803f80,
0x0,0x0,0x0,0x0,0x0,0x0,0x0,0x0,0x0,0x0,0x0,0x0,
0x0,0x0,0x0,0x0,0xbe480000,0xbf0ebec4,0xbf55bf35,0xbf7bbf6d,0x3f7b3f80,0x3f553f6d,0x3f0e3f35,0x3e483ec4,
0x3e480000,0x3f0e3ec4,0x3f553f35,0x3f7b3f6d,0xbf7bbf80,0xbf55bf6d,0xbf0ebf35,0xbe48bec4,0x3f7b3f80,0x3f553f6d,0x3f0e3f35,0x3e483ec4,
0x3e480000,0x3f0e3ec4,0x3f553f35,0x3f7b3f6d,0xbf7bbf80,0xbf55bf6d,0xbf0ebf35,0xbe48bec4,0xbe480000,0xbf0ebec4,0xbf55bf35,0xbf7bbf6d,
0x3f6d3f80,0x3ec43f35,0xbec40000,0xbf6dbf35,0xbf6dbf80,0xbec4bf35,0x3ec40000,0x3f6d3f35,0x3f6d3f80,0x3ec43f35,0xbec40000,0xbf6dbf35,
0xbf6dbf80,0xbec4bf35,0x3ec40000,0x3f6d3f35,0x3ec40000,0x3f6d3f35,0x3f6d3f80,0x3ec43f35,0xbec40000,0xbf6dbf35,0xbf6dbf80,0xbec4bf35,
0x3ec40000,0x3f6d3f35,0x3f6d3f80,0x3ec43f35,0xbec40000,0xbf6dbf35,0xbf6dbf80,0xbec4bf35,0xbf0e0000,0xbf7bbf6d,0xbe48bf35,0x3f553ec4,
0xbf55bf80,0x3e48bec4,0x3f7b3f35,0x3f0e3f6d,0x3f0e0000,0x3f7b3f6d,0x3e483f35,0xbf55bec4,0x3f553f80,0xbe483ec4,0xbf7bbf35,0xbf0ebf6d,
0x3f553f80,0xbe483ec4,0xbf7bbf35,0xbf0ebf6d,0xbf0e0000,0xbf7bbf6d,0xbe48bf35,0x3f553ec4,0xbf55bf80,0x3e48bec4,0x3f7b3f35,0x3f0e3f6d,
0x3f0e0000,0x3f7b3f6d,0x3e483f35,0xbf55bec4,0x3f350000,0x3f353f80,0xbf350000,0xbf35bf80,0x3f350000,0x3f353f80,0xbf350000,0xbf35bf80,
0x3f350000,0x3f353f80,0xbf350000,0xbf35bf80,0x3f350000,0x3f353f80,0xbf350000,0xbf35bf80,0x3f353f80,0xbf350000,0xbf35bf80,0x3f350000,
0x3f353f80,0xbf350000,0xbf35bf80,0x3f350000,0x3f353f80,0xbf350000,0xbf35bf80,0x3f350000,0x3f353f80,0xbf350000,0xbf35bf80,0x3f350000,
0x3f0e3f80,0xbf7bbec4,0x3e48bf35,0x3f553f6d,0x3f550000,0x3e483f6d,0xbf7bbf35,0x3f0ebec4,0xbf0ebf80,0x3f7b3ec4,0xbe483f35,0xbf55bf6d,
0xbf550000,0xbe48bf6d,0x3f7b3f35,0xbf0e3ec4,0xbf550000,0xbe48bf6d,0x3f7b3f35,0xbf0e3ec4,0x3f0e3f80,0xbf7bbec4,0x3e48bf35,0x3f553f6d,
0x3f550000,0x3e483f6d,0xbf7bbf35,0x3f0ebec4,0xbf0ebf80,0x3f7b3ec4,0xbe483f35,0xbf55bf6d,0x3f6d0000,0xbec43f35,0xbec4bf80,0x3f6d3f35,
0xbf6d0000,0x3ec4bf35,0x3ec43f80,0xbf6dbf35,0x3f6d0000,0xbec43f35,0xbec4bf80,0x3f6d3f35,0xbf6d0000,0x3ec4bf35,0x3ec43f80,0xbf6dbf35,
0x3ec43f80,0xbf6dbf35,0x3f6d0000,0xbec43f35,0xbec4bf80,0x3f6d3f35,0xbf6d0000,0x3ec4bf35,0x3ec43f80,0xbf6dbf35,0x3f6d0000,0xbec43f35,
0xbec4bf80,0x3f6d3f35,0xbf6d0000,0x3ec4bf35,0x3e483f80,0xbf0ebf6d,0x3f553f35,0xbf7bbec4,0xbf7b0000,0x3f55bec4,0xbf0e3f35,0x3e48bf6d,
0xbe48bf80,0x3f0e3f6d,0xbf55bf35,0x3f7b3ec4,0x3f7b0000,0xbf553ec4,0x3f0ebf35,0xbe483f6d,0xbf7b0000,0x3f55bec4,0xbf0e3f35,0x3e48bf6d,
0xbe48bf80,0x3f0e3f6d,0xbf55bf35,0x3f7b3ec4,0x3f7b0000,0xbf553ec4,0x3f0ebf35,0xbe483f6d,0x3e483f80,0xbf0ebf6d,0x3f553f35,0xbf7bbec4,
0x3f80,0xbf80,0x3f80,0xbf80,0x3f80,0xbf80,0x3f80,0xbf80,0x3f80,0xbf80,0x3f80,0xbf80,
0x3f80,0xbf80,0x3f80,0xbf80,0x3f800000,0xbf800000,0x3f800000,0xbf800000,0x3f800000,0xbf800000,0x3f800000,0xbf800000,
0x3f800000,0xbf800000,0x3f800000,0xbf800000,0x3f800000,0xbf800000,0x3f800000,0xbf800000,0xbf7b0000,0x3f553ec4,0xbf0ebf35,0x3e483f6d,
0xbe483f80,0x3f0ebf6d,0xbf553f35,0x3f7bbec4,0x3f7b0000,0xbf55bec4,0x3f0e3f35,0xbe48bf6d,0x3e48bf80,0xbf0e3f6d,0x3f55bf35,0xbf7b3ec4,
0xbe483f80,0x3f0ebf6d,0xbf553f35,0x3f7bbec4,0x3f7b0000,0xbf55bec4,0x3f0e3f35,0xbe48bf6d,0x3e48bf80,0xbf0e3f6d,0x3f55bf35,0xbf7b3ec4,
0xbf7b0000,0x3f553ec4,0xbf0ebf35,0x3e483f6d,0xbec43f80,0x3f6dbf35,0xbf6d0000,0x3ec43f35,0x3ec4bf80,0xbf6d3f35,0x3f6d0000,0xbec4bf35,
0xbec43f80,0x3f6dbf35,0xbf6d0000,0x3ec43f35,0x3ec4bf80,0xbf6d3f35,0x3f6d0000,0xbec4bf35,0x3f6d0000,0xbec4bf35,0xbec43f80,0x3f6dbf35,
0xbf6d0000,0x3ec43f35,0x3ec4bf80,0xbf6d3f35,0x3f6d0000,0xbec4bf35,0xbec43f80,0x3f6dbf35,0xbf6d0000,0x3ec43f35,0x3ec4bf80,0xbf6d3f35,
0xbf550000,0xbe483f6d,0x3f7bbf35,0xbf0ebec4,0x3f0ebf80,0xbf7b3ec4,0x3e483f35,0x3f55bf6d,0x3f550000,0x3e48bf6d,0xbf7b3f35,0x3f0e3ec4,
0xbf0e3f80,0x3f7bbec4,0xbe48bf35,0xbf553f6d,0xbf0e3f80,0x3f7bbec4,0xbe48bf35,0xbf553f6d,0xbf550000,0xbe483f6d,0x3f7bbf35,0xbf0ebec4,
0x3f0ebf80,0xbf7b3ec4,0x3e483f35,0x3f55bf6d,0x3f550000,0x3e48bf6d,0xbf7b3f35,0x3f0e3ec4,0x3f350000,0x3f35bf80,0xbf350000,0xbf353f80,
0x3f350000,0x3f35bf80,0xbf350000,0xbf353f80,0x3f350000,0x3f35bf80,0xbf350000,0xbf353f80,0x3f350000,0x3f35bf80,0xbf350000,0xbf353f80,
0xbf353f80,0x3f350000,0x3f35bf80,0xbf350000,0xbf353f80,0x3f350000,0x3f35bf80,0xbf350000,0xbf353f80,0x3f350000,0x3f35bf80,0xbf350000,
0xbf353f80,0x3f350000,0x3f35bf80,0xbf350000,0xbf553f80,0x3e483ec4,0x3f7bbf35,0x3f0ebf6d,0x3f0e0000,0x3f7bbf6d,0x3e48bf35,0xbf553ec4,
0x3f55bf80,0xbe48bec4,0xbf7b3f35,0xbf0e3f6d,0xbf0e0000,0xbf7b3f6d,0xbe483f35,0x3f55bec4,0xbf0e0000,0xbf7b3f6d,0xbe483f35,0x3f55bec4,
0xbf553f80,0x3e483ec4,0x3f7bbf35,0x3f0ebf6d,0x3f0e0000,0x3f7bbf6d,0x3e48bf35,0xbf553ec4,0x3f55bf80,0xbe48bec4,0xbf7b3f35,0xbf0e3f6d,
0x3ec40000,0x3f6dbf35,0x3f6dbf80,0x3ec4bf35,0xbec40000,0xbf6d3f35,0xbf6d3f80,0xbec43f35,0x3ec40000,0x3f6dbf35,0x3f6dbf80,0x3ec4bf35,
0xbec40000,0xbf6d3f35,0xbf6d3f80,0xbec43f35,0xbf6d3f80,0xbec43f35,0x3ec40000,0x3f6dbf35,0x3f6dbf80,0x3ec4bf35,0xbec40000,0xbf6d3f35,
0xbf6d3f80,0xbec43f35,0x3ec40000,0x3f6dbf35,0x3f6dbf80,0x3ec4bf35,0xbec40000,0xbf6d3f35,0xbf7b3f80,0xbf553f6d,0xbf0e3f35,0xbe483ec4,
0xbe480000,0xbf0e3ec4,0xbf553f35,0xbf7b3f6d,0x3f7bbf80,0x3f55bf6d,0x3f0ebf35,0x3e48bec4,0x3e480000,0x3f0ebec4,0x3f55bf35,0x3f7bbf6d,
0xbe480000,0xbf0e3ec4,0xbf553f35,0xbf7b3f6d,0x3f7bbf80,0x3f55bf6d,0x3f0ebf35,0x3e48bec4,0x3e480000,0x3f0ebec4,0x3f55bf35,0x3f7bbf6d,
0xbf7b3f80,0xbf553f6d,0xbf0e3f35,0xbe483ec4,0xbf803f80,0xbf803f80,0xbf803f80,0xbf803f80,0xbf803f80,0xbf803f80,0xbf803f80,0xbf803f80,
0xbf803f80,0xbf803f80,0xbf803f80,0xbf803f80,0xbf803f80,0xbf803f80,0xbf803f80,0xbf803f80,0x0,0x0,0x0,0x0,
0x0,0x0,0x0,0x0,0x0,0x0,0x0,0x0,0x0,0x0,0x0,0x0,
0x3e480000,0x3f0ebec4,0x3f55bf35,0x3f7bbf6d,0xbf7b3f80,0xbf553f6d,0xbf0e3f35,0xbe483ec4,0xbe480000,0xbf0e3ec4,0xbf553f35,0xbf7b3f6d,
0x3f7bbf80,0x3f55bf6d,0x3f0ebf35,0x3e48bec4,0xbf7b3f80,0xbf553f6d,0xbf0e3f35,0xbe483ec4,0xbe480000,0xbf0e3ec4,0xbf553f35,0xbf7b3f6d,
0x3f7bbf80,0x3f55bf6d,0x3f0ebf35,0x3e48bec4,0x3e480000,0x3f0ebec4,0x3f55bf35,0x3f7bbf6d,0xbf6d3f80,0xbec43f35,0x3ec40000,0x3f6dbf35,
0x3f6dbf80,0x3ec4bf35,0xbec40000,0xbf6d3f35,0xbf6d3f80,0xbec43f35,0x3ec40000,0x3f6dbf35,0x3f6dbf80,0x3ec4bf35,0xbec40000,0xbf6d3f35,
0xbec40000,0xbf6d3f35,0xbf6d3f80,0xbec43f35,0x3ec40000,0x3f6dbf35,0x3f6dbf80,0x3ec4bf35,0xbec40000,0xbf6d3f35,0xbf6d3f80,0xbec43f35,
0x3ec40000,0x3f6dbf35,0x3f6dbf80,0x3ec4bf35,0x3f0e0000,0x3f7bbf6d,0x3e48bf35,0xbf553ec4,0x3f55bf80,0xbe48bec4,0xbf7b3f35,0xbf0e3f6d,
0xbf0e0000,0xbf7b3f6d,0xbe483f35,0x3f55bec4,0xbf553f80,0x3e483ec4,0x3f7bbf35,0x3f0ebf6d,0xbf553f80,0x3e483ec4,0x3f7bbf35,0x3f0ebf6d,
0x3f0e0000,0x3f7bbf6d,0x3e48bf35,0xbf553ec4,0x3f55bf80,0xbe48bec4,0xbf7b3f35,0xbf0e3f6d,0xbf0e0000,0xbf7b3f6d,0xbe483f35,0x3f55bec4,
0xbf350000,0xbf353f80,0x3f350000,0x3f35bf80,0xbf350000,0xbf353f80,0x3f350000,0x3f35bf80,0xbf350000,0xbf353f80,0x3f350000,0x3f35bf80,
0xbf350000,0xbf353f80,0x3f350000,0x3f35bf80,0xbf353f80,0x3f350000,0x3f35bf80,0xbf350000,0xbf353f80,0x3f350000,0x3f35bf80,0xbf350000,
0xbf353f80,0x3f350000,0x3f35bf80,0xbf350000,0xbf353f80,0x3f350000,0x3f35bf80,0xbf350000,0xbf0e3f80,0x3f7bbec4,0xbe48bf35,0xbf553f6d,
0xbf550000,0xbe483f6d,0x3f7bbf35,0xbf0ebec4,0x3f0ebf80,0xbf7b3ec4,0x3e483f35,0x3f55bf6d,0x3f550000,0x3e48bf6d,0xbf7b3f35,0x3f0e3ec4,
0x3f550000,0x3e48bf6d,0xbf7b3f35,0x3f0e3ec4,0xbf0e3f80,0x3f7bbec4,0xbe48bf35,0xbf553f6d,0xbf550000,0xbe483f6d,0x3f7bbf35,0xbf0ebec4,
0x3f0ebf80,0xbf7b3ec4,0x3e483f35,0x3f55bf6d,0xbf6d0000,0x3ec43f35,0x3ec4bf80,0xbf6d3f35,0x3f6d0000,0xbec4bf35,0xbec43f80,0x3f6dbf35,
0xbf6d0000,0x3ec43f35,0x3ec4bf80,0xbf6d3f35,0x3f6d0000,0xbec4bf35,0xbec43f80,0x3f6dbf35,0xbec43f80,0x3f6dbf35,0xbf6d0000,0x3ec43f35,
0x3ec4bf80,0xbf6d3f35,0x3f6d0000,0xbec4bf35,0xbec43f80,0x3f6dbf35,0xbf6d0000,0x3ec43f35,0x3ec4bf80,0xbf6d3f35,0x3f6d0000,0xbec4bf35,
0xbe483f80,0x3f0ebf6d,0xbf553f35,0x3f7bbec4,0x3f7b0000,0xbf55bec4,0x3f0e3f35,0xbe48bf6d,0x3e48bf80,0xbf0e3f6d,0x3f55bf35,0xbf7b3ec4,
0xbf7b0000,0x3f553ec4,0xbf0ebf35,0x3e483f6d,0x3f7b0000,0xbf55bec4,0x3f0e3f35,0xbe48bf6d,0x3e48bf80,0xbf0e3f6d,0x3f55bf35,0xbf7b3ec4,
0xbf7b0000,0x3f553ec4,0xbf0ebf35,0x3e483f6d,0xbe483f80,0x3f0ebf6d,0xbf553f35,0x3f7bbec4,0x3f80,0xbf80,0x3f80,0xbf80,
0x3f80,0xbf80,0x3f80,0xbf80,0x3f80,0xbf80,0x3f80,0xbf80,0x3f80,0xbf80,0x3f80,0xbf80,
0xbf800000,0x3f800000,0xbf800000,0x3f800000,0xbf800000,0x3f800000,0xbf800000,0x3f800000,0xbf800000,0x3f800000,0xbf800000,0x3f800000,
0xbf800000,0x3f800000,0xbf800000,0x3f800000,0x3f7b0000,0xbf553ec4,0x3f0ebf35,0xbe483f6d,0x3e483f80,0xbf0ebf6d,0x3f553f35,0xbf7bbec4,
0xbf7b0000,0x3f55bec4,0xbf0e3f35,0x3e48bf6d,0xbe48bf80,0x3f0e3f6d,0xbf55bf35,0x3f7b3ec4,0x3e483f80,0xbf0ebf6d,0x3f553f35,0xbf7bbec4,
0xbf7b0000,0x3f55bec4,0xbf0e3f35,0x3e48bf6d,0xbe48bf80,0x3f0e3f6d,0xbf55bf35,0x3f7b3ec4,0x3f7b0000,0xbf553ec4,0x3f0ebf35,0xbe483f6d,
0x3ec43f80,0xbf6dbf35,0x3f6d0000,0xbec43f35,0xbec4bf80,0x3f6d3f35,0xbf6d0000,0x3ec4bf35,0x3ec43f80,0xbf6dbf35,0x3f6d0000,0xbec43f35,
0xbec4bf80,0x3f6d3f35,0xbf6d0000,0x3ec4bf35,0xbf6d0000,0x3ec4bf35,0x3ec43f80,0xbf6dbf35,0x3f6d0000,0xbec43f35,0xbec4bf80,0x3f6d3f35,
0xbf6d0000,0x3ec4bf35,0x3ec43f80,0xbf6dbf35,0x3f6d0000,0xbec43f35,0xbec4bf80,0x3f6d3f35,0x3f550000,0x3e483f6d,0xbf7bbf35,0x3f0ebec4,
0xbf0ebf80,0x3f7b3ec4,0xbe483f35,0xbf55bf6d,0xbf550000,0xbe48bf6d,0x3f7b3f35,0xbf0e3ec4,0x3f0e3f80,0xbf7bbec4,0x3e48bf35,0x3f553f6d,
0x3f0e3f80,0xbf7bbec4,0x3e48bf35,0x3f553f6d,0x3f550000,0x3e483f6d,0xbf7bbf35,0x3f0ebec4,0xbf0ebf80,0x3f7b3ec4,0xbe483f35,0xbf55bf6d,
0xbf550000,0xbe48bf6d,0x3f7b3f35,0xbf0e3ec4,0xbf350000,0xbf35bf80,0x3f350000,0x3f353f80,0xbf350000,0xbf35bf80,0x3f350000,0x3f353f80,
0xbf350000,0xbf35bf80,0x3f350000,0x3f353f80,0xbf350000,0xbf35bf80,0x3f350000,0x3f353f80,0x3f353f80,0xbf350000,0xbf35bf80,0x3f350000,
0x3f353f80,0xbf350000,0xbf35bf80,0x3f350000,0x3f353f80,0xbf350000,0xbf35bf80,0x3f350000,0x3f353f80,0xbf350000,0xbf35bf80,0x3f350000,
0x3f553f80,0xbe483ec4,0xbf7bbf35,0xbf0ebf6d,0xbf0e0000,0xbf7bbf6d,0xbe48bf35,0x3f553ec4,0xbf55bf80,0x3e48bec4,0x3f7b3f35,0x3f0e3f6d,
0x3f0e0000,0x3f7b3f6d,0x3e483f35,0xbf55bec4,0x3f0e0000,0x3f7b3f6d,0x3e483f35,0xbf55bec4,0x3f553f80,0xbe483ec4,0xbf7bbf35,0xbf0ebf6d,
0xbf0e0000,0xbf7bbf6d,0xbe48bf35,0x3f553ec4,0xbf55bf80,0x3e48bec4,0x3f7b3f35,0x3f0e3f6d,0xbec40000,0xbf6dbf35,0xbf6dbf80,0xbec4bf35,
0x3ec40000,0x3f6d3f35,0x3f6d3f80,0x3ec43f35,0xbec40000,0xbf6dbf35,0xbf6dbf80,0xbec4bf35,0x3ec40000,0x3f6d3f35,0x3f6d3f80,0x3ec43f35,
0x3f6d3f80,0x3ec43f35,0xbec40000,0xbf6dbf35,0xbf6dbf80,0xbec4bf35,0x3ec40000,0x3f6d3f35,0x3f6d3f80,0x3ec43f35,0xbec40000,0xbf6dbf35,
0xbf6dbf80,0xbec4bf35,0x3ec40000,0x3f6d3f35,0x3f7b3f80,0x3f553f6d,0x3f0e3f35,0x3e483ec4,0x3e480000,0x3f0e3ec4,0x3f553f35,0x3f7b3f6d,
0xbf7bbf80,0xbf55bf6d,0xbf0ebf35,0xbe48bec4,0xbe480000,0xbf0ebec4,0xbf55bf35,0xbf7bbf6d,0x3e480000,0x3f0e3ec4,0x3f553f35,0x3f7b3f6d,
0xbf7bbf80,0xbf55bf6d,0xbf0ebf35,0xbe48bec4,0xbe480000,0xbf0ebec4,0xbf55bf35,0xbf7bbf6d,0x3f7b3f80,0x3f553f6d,0x3f0e3f35,0x3e483ec4,
0x80008000,0x80008000,0x80008000,0x80008000,0x80008000,0x80008000,0x80008000,0x80008000,0x80008000,0x80008000,0x80008000,0x80008000,
0x80008000,0x80008000,0x80008000,0x80008000,0x3f803f80,0x3f803f80,0x3f803f80,0x3f803f80,0x3f803f80,0x3f803f80,0x3f803f80,0x3f803f80,
0x3f803f80,0x3f803f80,0x3f803f80,0x3f803f80,0x3f803f80,0x3f803f80,0x3f803f80,0x3f803f80,0xbf7bbf80,0xbf55bf6d,0xbf0ebf35,0xbe48bec4,
0xbe488000,0xbf0ebec4,0xbf55bf35,0xbf7bbf6d,0x3f7b3f80,0x3f553f6d,0x3f0e3f35,0x3e483ec4,0x3e488000,0x3f0e3ec4,0x3f553f35,0x3f7b3f6d,
0xbe480000,0xbf0ebec4,0xbf55bf35,0xbf7bbf6d,0x3f7b3f80,0x3f553f6d,0x3f0e3f35,0x3e483ec4,0x3e480000,0x3f0e3ec4,0x3f553f35,0x3f7b3f6d,
0xbf7bbf80,0xbf55bf6d,0xbf0ebf35,0xbe48bec4,0xbec48000,0xbf6dbf35,0xbf6dbf80,0xbec4bf35,0x3ec48000,0x3f6d3f35,0x3f6d3f80,0x3ec43f35,
0xbec48000,0xbf6dbf35,0xbf6dbf80,0xbec4bf35,0x3ec48000,0x3f6d3f35,0x3f6d3f80,0x3ec43f35,0x3f6d3f80,0x3ec43f35,0xbec40000,0xbf6dbf35,
0xbf6dbf80,0xbec4bf35,0x3ec40000,0x3f6d3f35,0x3f6d3f80,0x3ec43f35,0xbec40000,0xbf6dbf35,0xbf6dbf80,0xbec4bf35,0x3ec40000,0x3f6d3f35,
0xbf55bf80,0x3e48bec4,0x3f7b3f35,0x3f0e3f6d,0x3f0e8000,0x3f7b3f6d,0x3e483f35,0xbf55bec4,0x3f553f80,0xbe483ec4,0xbf7bbf35,0xbf0ebf6d,
0xbf0e8000,0xbf7bbf6d,0xbe48bf35,0x3f553ec4,0xbf0e0000,0xbf7bbf6d,0xbe48bf35,0x3f553ec4,0xbf55bf80,0x3e48bec4,0x3f7b3f35,0x3f0e3f6d,
0x3f0e0000,0x3f7b3f6d,0x3e483f35,0xbf55bec4,0x3f553f80,0xbe483ec4,0xbf7bbf35,0xbf0ebf6d,0x3f353f80,0xbf350000,0xbf35bf80,0x3f350000,
0x3f353f80,0xbf350000,0xbf35bf80,0x3f350000,0x3f353f80,0xbf350000,0xbf35bf80,0x3f350000,0x3f353f80,0xbf350000,0xbf35bf80,0x3f350000,
0xbf358000,0xbf35bf80,0x3f358000,0x3f353f80,0xbf358000,0xbf35bf80,0x3f358000,0x3f353f80,0xbf358000,0xbf35bf80,0x3f358000,0x3f353f80,
0xbf358000,0xbf35bf80,0x3f358000,0x3f353f80,0xbf550000,0xbe48bf6d,0x3f7b3f35,0xbf0e3ec4,0x3f0e3f80,0xbf7bbec4,0x3e48bf35,0x3f553f6d,
0x3f550000,0x3e483f6d,0xbf7bbf35,0x3f0ebec4,0xbf0ebf80,0x3f7b3ec4,0xbe483f35,0xbf55bf6d,0xbf0ebf80,0x3f7b3ec4,0xbe483f35,0xbf55bf6d,
0xbf558000,0xbe48bf6d,0x3f7b3f35,0xbf0e3ec4,0x3f0e3f80,0xbf7bbec4,0x3e48bf35,0x3f553f6d,0x3f558000,0x3e483f6d,0xbf7bbf35,0x3f0ebec4,
0x3ec43f80,0xbf6dbf35,0x3f6d0000,0xbec43f35,0xbec4bf80,0x3f6d3f35,0xbf6d0000,0x3ec4bf35,0x3ec43f80,0xbf6dbf35,0x3f6d0000,0xbec43f35,
0xbec4bf80,0x3f6d3f35,0xbf6d0000,0x3ec4bf35,0xbf6d8000,0x3ec4bf35,0x3ec43f80,0xbf6dbf35,0x3f6d8000,0xbec43f35,0xbec4bf80,0x3f6d3f35,
0xbf6d8000,0x3ec4bf35,0x3ec43f80,0xbf6dbf35,0x3f6d8000,0xbec43f35,0xbec4bf80,0x3f6d3f35,0xbf7b0000,0x3f55bec4,0xbf0e3f35,0x3e48bf6d,
0xbe48bf80,0x3f0e3f6d,0xbf55bf35,0x3f7b3ec4,0x3f7b0000,0xbf553ec4,0x3f0ebf35,0xbe483f6d,0x3e483f80,0xbf0ebf6d,0x3f553f35,0xbf7bbec4,
0xbe48bf80,0x3f0e3f6d,0xbf55bf35,0x3f7b3ec4,0x3f7b8000,0xbf553ec4,0x3f0ebf35,0xbe483f6d,0x3e483f80,0xbf0ebf6d,0x3f553f35,0xbf7bbec4,
0xbf7b8000,0x3f55bec4,0xbf0e3f35,0x3e48bf6d,0xbf808000,0x3f808000,0xbf808000,0x3f808000,0xbf808000,0x3f808000,0xbf808000,0x3f808000,
0xbf808000,0x3f808000,0xbf808000,0x3f808000,0xbf808000,0x3f808000,0xbf808000,0x3f808000,0x3f80,0xbf80,0x3f80,0xbf80,
0x3f80,0xbf80,0x3f80,0xbf80,0x3f80,0xbf80,0x3f80,0xbf80,0x3f80,0xbf80,0x3f80,0xbf80,
0x3e48bf80,0xbf0e3f6d,0x3f55bf35,0xbf7b3ec4,0xbf7b8000,0x3f553ec4,0xbf0ebf35,0x3e483f6d,0xbe483f80,0x3f0ebf6d,0xbf553f35,0x3f7bbec4,
0x3f7b8000,0xbf55bec4,0x3f0e3f35,0xbe48bf6d,0xbf7b0000,0x3f553ec4,0xbf0ebf35,0x3e483f6d,0xbe483f80,0x3f0ebf6d,0xbf553f35,0x3f7bbec4,
0x3f7b0000,0xbf55bec4,0x3f0e3f35,0xbe48bf6d,0x3e48bf80,0xbf0e3f6d,0x3f55bf35,0xbf7b3ec4,0xbf6d8000,0x3ec43f35,0x3ec4bf80,0xbf6d3f35,
0x3f6d8000,0xbec4bf35,0xbec43f80,0x3f6dbf35,0xbf6d8000,0x3ec43f35,0x3ec4bf80,0xbf6d3f35,0x3f6d8000,0xbec4bf35,0xbec43f80,0x3f6dbf35,
0xbec43f80,0x3f6dbf35,0xbf6d0000,0x3ec43f35,0x3ec4bf80,0xbf6d3f35,0x3f6d0000,0xbec4bf35,0xbec43f80,0x3f6dbf35,0xbf6d0000,0x3ec43f35,
0x3ec4bf80,0xbf6d3f35,0x3f6d0000,0xbec4bf35,0x3f0ebf80,0xbf7b3ec4,0x3e483f35,0x3f55bf6d,0x3f558000,0x3e48bf6d,0xbf7b3f35,0x3f0e3ec4,
0xbf0e3f80,0x3f7bbec4,0xbe48bf35,0xbf553f6d,0xbf558000,0xbe483f6d,0x3f7bbf35,0xbf0ebec4,0xbf550000,0xbe483f6d,0x3f7bbf35,0xbf0ebec4,
0x3f0ebf80,0xbf7b3ec4,0x3e483f35,0x3f55bf6d,0x3f550000,0x3e48bf6d,0xbf7b3f35,0x3f0e3ec4,0xbf0e3f80,0x3f7bbec4,0xbe48bf35,0xbf553f6d,
0xbf353f80,0x3f350000,0x3f35bf80,0xbf350000,0xbf353f80,0x3f350000,0x3f35bf80,0xbf350000,0xbf353f80,0x3f350000,0x3f35bf80,0xbf350000,
0xbf353f80,0x3f350000,0x3f35bf80,0xbf350000,0xbf358000,0xbf353f80,0x3f358000,0x3f35bf80,0xbf358000,0xbf353f80,0x3f358000,0x3f35bf80,
0xbf358000,0xbf353f80,0x3f358000,0x3f35bf80,0xbf358000,0xbf353f80,0x3f358000,0x3f35bf80,0xbf0e0000,0xbf7b3f6d,0xbe483f35,0x3f55bec4,
0xbf553f80,0x3e483ec4,0x3f7bbf35,0x3f0ebf6d,0x3f0e0000,0x3f7bbf6d,0x3e48bf35,0xbf553ec4,0x3f55bf80,0xbe48bec4,0xbf7b3f35,0xbf0e3f6d,
0x3f55bf80,0xbe48bec4,0xbf7b3f35,0xbf0e3f6d,0xbf0e8000,0xbf7b3f6d,0xbe483f35,0x3f55bec4,0xbf553f80,0x3e483ec4,0x3f7bbf35,0x3f0ebf6d,
0x3f0e8000,0x3f7bbf6d,0x3e48bf35,0xbf553ec4,0xbf6d3f80,0xbec43f35,0x3ec40000,0x3f6dbf35,0x3f6dbf80,0x3ec4bf35,0xbec40000,0xbf6d3f35,
0xbf6d3f80,0xbec43f35,0x3ec40000,0x3f6dbf35,0x3f6dbf80,0x3ec4bf35,0xbec40000,0xbf6d3f35,0xbec48000,0xbf6d3f35,0xbf6d3f80,0xbec43f35,
0x3ec48000,0x3f6dbf35,0x3f6dbf80,0x3ec4bf35,0xbec48000,0xbf6d3f35,0xbf6d3f80,0xbec43f35,0x3ec48000,0x3f6dbf35,0x3f6dbf80,0x3ec4bf35,
0xbe480000,0xbf0e3ec4,0xbf553f35,0xbf7b3f6d,0x3f7bbf80,0x3f55bf6d,0x3f0ebf35,0x3e48bec4,0x3e480000,0x3f0ebec4,0x3f55bf35,0x3f7bbf6d,
0xbf7b3f80,0xbf553f6d,0xbf0e3f35,0xbe483ec4,0x3f7bbf80,0x3f55bf6d,0x3f0ebf35,0x3e48bec4,0x3e488000,0x3f0ebec4,0x3f55bf35,0x3f7bbf6d,
0xbf7b3f80,0xbf553f6d,0xbf0e3f35,0xbe483ec4,0xbe488000,0xbf0e3ec4,0xbf553f35,0xbf7b3f6d,0x80008000,0x80008000,0x80008000,0x80008000,
0x80008000,0x80008000,0x80008000,0x80008000,0x80008000,0x80008000,0x80008000,0x80008000,0x80008000,0x80008000,0x80008000,0x80008000,
0xbf803f80,0xbf803f80,0xbf803f80,0xbf803f80,0xbf803f80,0xbf803f80,0xbf803f80,0xbf803f80,0xbf803f80,0xbf803f80,0xbf803f80,0xbf803f80,
0xbf803f80,0xbf803f80,0xbf803f80,0xbf803f80,0x3f7bbf80,0x3f55bf6d,0x3f0ebf35,0x3e48bec4,0x3e488000,0x3f0ebec4,0x3f55bf35,0x3f7bbf6d,
0xbf7b3f80,0xbf553f6d,0xbf0e3f35,0xbe483ec4,0xbe488000,0xbf0e3ec4,0xbf553f35,0xbf7b3f6d,0x3e480000,0x3f0ebec4,0x3f55bf35,0x3f7bbf6d,
0xbf7b3f80,0xbf553f6d,0xbf0e3f35,0xbe483ec4,0xbe480000,0xbf0e3ec4,0xbf553f35,0xbf7b3f6d,0x3f7bbf80,0x3f55bf6d,0x3f0ebf35,0x3e48bec4,
0x3ec48000,0x3f6dbf35,0x3f6dbf80,0x3ec4bf35,0xbec48000,0xbf6d3f35,0xbf6d3f80,0xbec43f35,0x3ec48000,0x3f6dbf35,0x3f6dbf80,0x3ec4bf35,
0xbec48000,0xbf6d3f35,0xbf6d3f80,0xbec43f35,0xbf6d3f80,0xbec43f35,0x3ec40000,0x3f6dbf35,0x3f6dbf80,0x3ec4bf35,0xbec40000,0xbf6d3f35,
0xbf6d3f80,0xbec43f35,0x3ec40000,0x3f6dbf35,0x3f6dbf80,0x3ec4bf35,0xbec40000,0xbf6d3f35,0x3f55bf80,0xbe48bec4,0xbf7b3f35,0xbf0e3f6d,
0xbf0e8000,0xbf7b3f6d,0xbe483f35,0x3f55bec4,0xbf553f80,0x3e483ec4,0x3f7bbf35,0x3f0ebf6d,0x3f0e8000,0x3f7bbf6d,0x3e48bf35,0xbf553ec4,
0x3f0e0000,0x3f7bbf6d,0x3e48bf35,0xbf553ec4,0x3f55bf80,0xbe48bec4,0xbf7b3f35,0xbf0e3f6d,0xbf0e0000,0xbf7b3f6d,0xbe483f35,0x3f55bec4,
0xbf553f80,0x3e483ec4,0x3f7bbf35,0x3f0ebf6d,0xbf353f80,0x3f350000,0x3f35bf80,0xbf350000,0xbf353f80,0x3f350000,0x3f35bf80,0xbf350000,
0xbf353f80,0x3f350000,0x3f35bf80,0xbf350000,0xbf353f80,0x3f350000,0x3f35bf80,0xbf350000,0x3f358000,0x3f35bf80,0xbf358000,0xbf353f80,
0x3f358000,0x3f35bf80,0xbf358000,0xbf353f80,0x3f358000,0x3f35bf80,0xbf358000,0xbf353f80,0x3f358000,0x3f35bf80,0xbf358000,0xbf353f80,
0x3f550000,0x3e48bf6d,0xbf7b3f35,0x3f0e3ec4,0xbf0e3f80,0x3f7bbec4,0xbe48bf35,0xbf553f6d,0xbf550000,0xbe483f6d,0x3f7bbf35,0xbf0ebec4,
0x3f0ebf80,0xbf7b3ec4,0x3e483f35,0x3f55bf6d,0x3f0ebf80,0xbf7b3ec4,0x3e483f35,0x3f55bf6d,0x3f558000,0x3e48bf6d,0xbf7b3f35,0x3f0e3ec4,
0xbf0e3f80,0x3f7bbec4,0xbe48bf35,0xbf553f6d,0xbf558000,0xbe483f6d,0x3f7bbf35,0xbf0ebec4,0xbec43f80,0x3f6dbf35,0xbf6d0000,0x3ec43f35,
0x3ec4bf80,0xbf6d3f35,0x3f6d0000,0xbec4bf35,0xbec43f80,0x3f6dbf35,0xbf6d0000,0x3ec43f35,0x3ec4bf80,0xbf6d3f35,0x3f6d0000,0xbec4bf35,
0x3f6d8000,0xbec4bf35,0xbec43f80,0x3f6dbf35,0xbf6d8000,0x3ec43f35,0x3ec4bf80,0xbf6d3f35,0x3f6d8000,0xbec4bf35,0xbec43f80,0x3f6dbf35,
0xbf6d8000,0x3ec43f35,0x3ec4bf80,0xbf6d3f35,0x3f7b0000,0xbf55bec4,0x3f0e3f35,0xbe48bf6d,0x3e48bf80,0xbf0e3f6d,0x3f55bf35,0xbf7b3ec4,
0xbf7b0000,0x3f553ec4,0xbf0ebf35,0x3e483f6d,0xbe483f80,0x3f0ebf6d,0xbf553f35,0x3f7bbec4,0x3e48bf80,0xbf0e3f6d,0x3f55bf35,0xbf7b3ec4,
0xbf7b8000,0x3f553ec4,0xbf0ebf35,0x3e483f6d,0xbe483f80,0x3f0ebf6d,0xbf553f35,0x3f7bbec4,0x3f7b8000,0xbf55bec4,0x3f0e3f35,0xbe48bf6d,
0x3f808000,0xbf808000,0x3f808000,0xbf808000,0x3f808000,0xbf808000,0x3f808000,0xbf808000,0x3f808000,0xbf808000,0x3f808000,0xbf808000,
0x3f808000,0xbf808000,0x3f808000,0xbf808000,0x3f80,0xbf80,0x3f80,0xbf80,0x3f80,0xbf80,0x3f80,0xbf80,
0x3f80,0xbf80,0x3f80,0xbf80,0x3f80,0xbf80,0x3f80,0xbf80,0xbe48bf80,0x3f0e3f6d,0xbf55bf35,0x3f7b3ec4,
0x3f7b8000,0xbf553ec4,0x3f0ebf35,0xbe483f6d,0x3e483f80,0xbf0ebf6d,0x3f553f35,0xbf7bbec4,0xbf7b8000,0x3f55bec4,0xbf0e3f35,0x3e48bf6d,
0x3f7b0000,0xbf553ec4,0x3f0ebf35,0xbe483f6d,0x3e483f80,0xbf0ebf6d,0x3f553f35,0xbf7bbec4,0xbf7b0000,0x3f55bec4,0xbf0e3f35,0x3e48bf6d,
0xbe48bf80,0x3f0e3f6d,0xbf55bf35,0x3f7b3ec4,0x3f6d8000,0xbec43f35,0xbec4bf80,0x3f6d3f35,0xbf6d8000,0x3ec4bf35,0x3ec43f80,0xbf6dbf35,
0x3f6d8000,0xbec43f35,0xbec4bf80,0x3f6d3f35,0xbf6d8000,0x3ec4bf35,0x3ec43f80,0xbf6dbf35,0x3ec43f80,0xbf6dbf35,0x3f6d0000,0xbec43f35,
0xbec4bf80,0x3f6d3f35,0xbf6d0000,0x3ec4bf35,0x3ec43f80,0xbf6dbf35,0x3f6d0000,0xbec43f35,0xbec4bf80,0x3f6d3f35,0xbf6d0000,0x3ec4bf35,
0xbf0ebf80,0x3f7b3ec4,0xbe483f35,0xbf55bf6d,0xbf558000,0xbe48bf6d,0x3f7b3f35,0xbf0e3ec4,0x3f0e3f80,0xbf7bbec4,0x3e48bf35,0x3f553f6d,
0x3f558000,0x3e483f6d,0xbf7bbf35,0x3f0ebec4,0x3f550000,0x3e483f6d,0xbf7bbf35,0x3f0ebec4,0xbf0ebf80,0x3f7b3ec4,0xbe483f35,0xbf55bf6d,
0xbf550000,0xbe48bf6d,0x3f7b3f35,0xbf0e3ec4,0x3f0e3f80,0xbf7bbec4,0x3e48bf35,0x3f553f6d,0x3f353f80,0xbf350000,0xbf35bf80,0x3f350000,
0x3f353f80,0xbf350000,0xbf35bf80,0x3f350000,0x3f353f80,0xbf350000,0xbf35bf80,0x3f350000,0x3f353f80,0xbf350000,0xbf35bf80,0x3f350000,
0x3f358000,0x3f353f80,0xbf358000,0xbf35bf80,0x3f358000,0x3f353f80,0xbf358000,0xbf35bf80,0x3f358000,0x3f353f80,0xbf358000,0xbf35bf80,
0x3f358000,0x3f353f80,0xbf358000,0xbf35bf80,0x3f0e0000,0x3f7b3f6d,0x3e483f35,0xbf55bec4,0x3f553f80,0xbe483ec4,0xbf7bbf35,0xbf0ebf6d,
0xbf0e0000,0xbf7bbf6d,0xbe48bf35,0x3f553ec4,0xbf55bf80,0x3e48bec4,0x3f7b3f35,0x3f0e3f6d,0xbf55bf80,0x3e48bec4,0x3f7b3f35,0x3f0e3f6d,
0x3f0e8000,0x3f7b3f6d,0x3e483f35,0xbf55bec4,0x3f553f80,0xbe483ec4,0xbf7bbf35,0xbf0ebf6d,0xbf0e8000,0xbf7bbf6d,0xbe48bf35,0x3f553ec4,
0x3f6d3f80,0x3ec43f35,0xbec40000,0xbf6dbf35,0xbf6dbf80,0xbec4bf35,0x3ec40000,0x3f6d3f35,0x3f6d3f80,0x3ec43f35,0xbec40000,0xbf6dbf35,
0xbf6dbf80,0xbec4bf35,0x3ec40000,0x3f6d3f35,0x3ec48000,0x3f6d3f35,0x3f6d3f80,0x3ec43f35,0xbec48000,0xbf6dbf35,0xbf6dbf80,0xbec4bf35,
0x3ec48000,0x3f6d3f35,0x3f6d3f80,0x3ec43f35,0xbec48000,0xbf6dbf35,0xbf6dbf80,0xbec4bf35,0x3e480000,0x3f0e3ec4,0x3f553f35,0x3f7b3f6d,
0xbf7bbf80,0xbf55bf6d,0xbf0ebf35,0xbe48bec4,0xbe480000,0xbf0ebec4,0xbf55bf35,0xbf7bbf6d,0x3f7b3f80,0x3f553f6d,0x3f0e3f35,0x3e483ec4,
0xbf7bbf80,0xbf55bf6d,0xbf0ebf35,0xbe48bec4,0xbe488000,0xbf0ebec4,0xbf55bf35,0xbf7bbf6d,0x3f7b3f80,0x3f553f6d,0x3f0e3f35,0x3e483ec4,
0x3e488000,0x3f0e3ec4,0x3f553f35,0x3f7b3f6d,0x80003c00,0x80003c00,0x80003c00,0x80003c00,0x80003c00,0x80003c00,0x80003c00,0x80003c00,
0x80003c00,0x80003c00,0x80003c00,0x80003c00,0x80003c00,0x80003c00,0x80003c00,0x80003c00,0x80003c00,0x9e483c00,0xaa483bfe,0xab113bfd,
0xa2483c00,0xa4b63c00,0xabd93bfc,0xac513bfb,0xa6483bff,0xa7da3bff,0xacb53bfa,0xad1a3bf9,0xa8b63bff,0xa97f3bfe,0xad7e3bf8,0xade23bf7,
0x80003c00,0xa2483c00,0xae463bf6,0xaf0e3bf4,0xa6483bff,0xa8b63bff,0xafd63bf1,0xb04e3bed,0xaa483bfe,0xabd93bfc,0xb0b23bea,0xb1153be6,
0xacb53bfa,0xad7e3bf8,0xb1793be2,0xb1db3bdd,0x80003c00,0xa4b63c00,0xb0b23bea,0xb1473be4,0xa8b63bff,0xab113bfd,0xb1db3bdd,0xb26f3bd6,
0xacb53bfa,0xade23bf7,0xb3033bce,0xb3963bc6,0xaf0e3bf4,0xb01d3bef,0xb4143bbc,0xb45d3bb2,0x80003c00,0xa6483bff,0xb23e3bd9,0xb3033bce,
0xaa483bfe,0xacb53bfa,0xb3c63bc3,0xb4443bb6,0xae463bf6,0xafd63bf1,0xb4a53ba8,0xb5053b99,0xb0b23bea,0xb1793be2,0xb5643b88,0xb5c23b77,
0x80003c00,0xa7da3bff,0xb3c63bc3,0xb45d3bb2,0xabd93bfc,0xade23bf7,0xb4d53ba0,0xb54c3b8c,0xafd63bf1,0xb0e43be8,0xb5c23b77,0xb6373b5f,
0xb1db3bdd,0xb2d23bd1,0xb6aa3b46,0xb71b3b2b,0x80003c00,0xa8b63bff,0xb4a53ba8,0xb5343b91,0xacb53bfa,0xaf0e3bf4,0xb5c23b77,0xb64e3b5a,
0xb0b23bea,0xb1db3bdd,0xb6d73b3b,0xb75e3b1a,0xb3033bce,0xb4143bbc,0xb7e33af6,0xb8323ad0,0x80003c00,0xa97f3bfe,0xb5643b88,0xb6083b69,
0xad7e3bf8,0xb01d3bef,0xb6aa3b46,0xb7483b20,0xb1793be2,0xb2d23bd1,0xb7e33af6,0xb83d3ac9,0xb4143bbc,0xb4bd3ba4,0xb8873a99,0xb8ce3a65,
0x80003c00,0x80003c00,0x80003c00,0x80003c00,0x80003c00,0x80003c00,0x80003c00,0x80003c00,0x80003c00,0x80003c00,0x80003c00,0x80003c00,
0x80003c00,0x80003c00,0x80003c00,0x80003c00,0xae463bf6,0xaeaa3bf5,0xb0b23bea,0xb0e43be8,0xaf0e3bf4,0xaf723bf2,0xb1153be6,0xb1473be4,
0xafd63bf1,0xb01d3bef,0xb1793be2,0xb1aa3be0,0xb04e3bed,0xb0803bec,0xb1db3bdd,0xb20d3bdb,0xb23e3bd9,0xb2a13bd4,0xb4a53ba8,0xb4d53ba0,
0xb3033bce,0xb3653bc9,0xb5053b99,0xb5343b91,0xb3c63bc3,0xb4143bbc,0xb5643b88,0xb5933b80,0xb4443bb6,0xb4753baf,0xb5c23b77,0xb5f13b6e,
0xb4a53ba8,0xb4ed3b9d,0xb6d73b3b,0xb71b3b2b,0xb5343b91,0xb57c3b84,0xb75e3b1a,0xb7a13b08,0xb5c23b77,0xb6083b69,0xb7e33af6,0xb8123ae3,
0xb64e3b5a,0xb6933b4b,0xb8323ad0,0xb8523abc,0xb61f3b64,0xb67c3b50,0xb8723aa7,0xb89b3a8a,0xb6d73b3b,0xb7323b25,0xb8c43a6d,0xb8ec3a4f,
0xb78b3b0e,0xb7e33af6,0xb9133a2f,0xb93a3a0f,0xb81d3add,0xb8483ac2,0xb95f39ed,0xb98439cb,0xb78b3b0e,0xb7f93af0,0xb95f39ed,0xb98d39c3,
0xb8323ad0,0xb8673aae,0xb9ba3996,0xb9e53969,0xb89b3a8a,0xb8ce3a65,0xba0f393a,0xba373909,0xb9003a3f,0xb9303a17,0xba5e38d8,0xba8338a6,
0xb8723aa7,0xb8b03a7c,0xba2f3913,0xba5e38d8,0xb8ec3a4f,0xb9273a1f,0xba8a389b,0xbab5385d,0xb95f39ed,0xb99639ba,0xbadd381d,0xbb0237b7,
0xb9cb3984,0xb9fe394d,0xbb253732,0xbb4636aa,0xb9133a2f,0xb95639f6,0xbadd381d,0xbb0837a1,0xb99639ba,0xb9d4397b,0xbb303705,0xbb553665,
0xba0f393a,0xba4738f6,0xbb7735c2,0xbb95351d,0xba7c38b0,0xbaae3867,0xbbaf3475,0xbbc63396,0x80003c00,0xaa483bfe,0xb61f3b64,0xb6d73b3b,
0xae463bf6,0xb0b23bea,0xb78b3b0e,0xb81d3add,0xb23e3bd9,0xb3c63bc3,0xb8723aa7,0xb8c43a6d,0xb4a53ba8,0xb5643b88,0xb9133a2f,0xb95f39ed,
0x80003c00,0xab113bfd,0xb6d73b3b,0xb7a13b08,0xaf0e3bf4,0xb1473be4,0xb8323ad0,0xb8913a92,0xb3033bce,0xb45d3bb2,0xb8ec3a4f,0xb9433a07,
0xb5343b91,0xb6083b69,0xb99639ba,0xb9e53969,0x80003c00,0xabd93bfc,0xb78b3b0e,0xb8323ad0,0xafd63bf1,0xb1db3bdd,0xb89b3a8a,0xb9003a3f,
0xb3c63bc3,0xb4d53ba0,0xb95f39ed,0xb9ba3996,0xb5c23b77,0xb6aa3b46,0xba0f393a,0xba5e38d8,0x80003c00,0xac513bfb,0xb81d3add,0xb8913a92,
0xb04e3bed,0xb26f3bd6,0xb9003a3f,0xb96939e5,0xb4443bb6,0xb54c3b8c,0xb9cb3984,0xba27391d,0xb64e3b5a,0xb7483b20,0xba7c38b0,0xbac9383d,
0x80003c00,0xacb53bfa,0xb8723aa7,0xb8ec3a4f,0xb0b23bea,0xb3033bce,0xb95f39ed,0xb9cb3984,0xb4a53ba8,0xb5c23b77,0xba2f3913,0xba8a389b,
0xb6d73b3b,0xb7e33af6,0xbadd381d,0xbb253732,0x80003c00,0xad1a3bf9,0xb8c43a6d,0xb9433a07,0xb1153be6,0xb3963bc6,0xb9ba3996,0xba27391d,
0xb5053b99,0xb6373b5f,0xba8a389b,0xbae33812,0xb75e3b1a,0xb83d3ac9,0xbb303705,0xbb7235da,0x80003c00,0xad7e3bf8,0xb9133a2f,0xb99639ba,
0xb1793be2,0xb4143bbc,0xba0f393a,0xba7c38b0,0xb5643b88,0xb6aa3b46,0xbadd381d,0xbb303705,0xb7e33af6,0xb8873a99,0xbb7735c2,0xbbaf3475,
0x80003c00,0xade23bf7,0xb95f39ed,0xb9e53969,0xb1db3bdd,0xb45d3bb2,0xba5e38d8,0xbac9383d,0xb5c23b77,0xb71b3b2b,0xbb253732,0xbb7235da,
0xb8323ad0,0xb8ce3a65,0xbbaf3475,0xbbdb320d,0xb9a839a8,0xb9ed395f,0xbb64361f,0xbb883564,0xba2f3913,0xba6d38c4,0xbba834a5,0xbbc333c6,
0xbaa73872,0xbadd381d,0xbbd9323e,0xbbea30b2,0xbb0e378b,0xbb3b36d7,0xbbf62e46,0xbbfe2a48,0xba2f3913,0xba7438ba,0xbbc333c6,0xbbdb320d,
0xbab5385d,0xbaf037f9,0xbbed304e,0xbbf92d1a,0xbb253732,0xbb553665,0xbbff2648,0xbbffa7da,0xbb803593,0xbba434bd,0xbbf8ad7e,0xbbecb080,
0xbaa73872,0xbae93807,0xbbf62e46,0xbbff28b6,0xbb253732,0xbb5a364e,0xbbffa648,0xbbf8ad7e,0xbb883564,0xbbaf3475,0xbbeab0b2,0xbbd4b2a1,
0xbbce3303,0xbbe63115,0xbbb6b444,0xbb91b534,0xbb0e378b,0xbb4b3693,0xbbfeaa48,0xbbf2af72,0xbb803593,0xbbab348d,0xbbddb1db,0xbbc0b3f7,
0xbbce3303,0xbbe830e4,0xbb99b505,0xbb69b608,0xbbf82d7e,0xbc0024b6,0xbb30b705,0xbaf0b7f9,0xbb64361f,0xbb993505,0xbbd9b23e,0xbbb6b444,
0xbbc333c6,0xbbe23179,0xbb88b564,0xbb50b67c,0xbbf62e46,0xbbff2648,0xbb0eb78b,0xbac2b848,0xbbfeaa48,0xbbf1afd6,0xba6db8c4,0xba0fb93a,
0xbba834a5,0xbbd132d2,0xbb88b564,0xbb4bb693,0xbbed304e,0xbbfd2b11,0xbb02b7b7,0xbaaeb867,0xbbffa648,0xbbf5aeaa,0xba4fb8ec,0xb9e5b969,
0xbbddb1db,0xbbb9b42c,0xb972b9dc,0xb8f6ba47,0xbbd9323e,0xbbf42f0e,0xbb0eb78b,0xbab5b85d,0xbbff2648,0xbbfcabd9,0xba4fb8ec,0xb9dcb972,
0xbbeab0b2,0xbbc9b365,0xb95fb9ed,0xb8d8ba5e,0xbb99b505,0xbb5ab64e,0xb848bac2,0xb75ebb1a,0xbbf62e46,0xbc001e48,0xba6db8c4,0xb9f6b956,
0xbbf8ad7e,0xbbe0b1aa,0xb972b9dc,0xb8e2ba56,0xbbb6b444,0xbb7bb5ab,0xb848bac2,0xb748bb20,0xbb30b705,0xbad6b828,0xb5f1bb6e,0xb48dbbab,
0x80003c00,0xae463bf6,0xb9a839a8,0xba2f3913,0xb23e3bd9,0xb4a53ba8,0xbaa73872,0xbb0e378b,0xb61f3b64,0xb78b3b0e,0xbb64361f,0xbba834a5,
0xb8723aa7,0xb9133a2f,0xbbd9323e,0xbbf62e46,0x80003c00,0xaeaa3bf5,0xb9ed395f,0xba7438ba,0xb2a13bd4,0xb4ed3b9d,0xbae93807,0xbb4b3693,
0xb67c3b50,0xb7f93af0,0xbb993505,0xbbd132d2,0xb8b03a7c,0xb95639f6,0xbbf42f0e,0xbc001e48,0x80003c00,0xaf0e3bf4,0xba2f3913,0xbab5385d,
0xb3033bce,0xb5343b91,0xbb253732,0xbb803593,0xb6d73b3b,0xb8323ad0,0xbbc333c6,0xbbed304e,0xb8ec3a4f,0xb99639ba,0xbbff2648,0xbbf8ad7e,
0x80003c00,0xaf723bf2,0xba6d38c4,0xbaf037f9,0xb3653bc9,0xb57c3b84,0xbb5a364e,0xbbab348d,0xb7323b25,0xb8673aae,0xbbe23179,0xbbfd2b11,
0xb9273a1f,0xb9d4397b,0xbbfcabd9,0xbbe0b1aa,0x80003c00,0xafd63bf1,0xbaa73872,0xbb253732,0xb3c63bc3,0xb5c23b77,0xbb883564,0xbbce3303,
0xb78b3b0e,0xb89b3a8a,0xbbf62e46,0xbbffa648,0xb95f39ed,0xba0f393a,0xbbeab0b2,0xbbb6b444,0x80003c00,0xb01d3bef,0xbadd381d,0xbb553665,
0xb4143bbc,0xb6083b69,0xbbaf3475,0xbbe830e4,0xb7e33af6,0xb8ce3a65,0xbbff2648,0xbbf5aeaa,0xb99639ba,0xba4738f6,0xbbc9b365,0xbb7bb5ab,
0x80003c00,0xb04e3bed,0xbb0e378b,0xbb803593,0xb4443bb6,0xb64e3b5a,0xbbce3303,0xbbf82d7e,0xb81d3add,0xb9003a3f,0xbbfeaa48,0xbbddb1db,
0xb9cb3984,0xba7c38b0,0xbb99b505,0xbb30b705,0x80003c00,0xb0803bec,0xbb3b36d7,0xbba434bd,0xb4753baf,0xb6933b4b,0xbbe63115,0xbc0024b6,
0xb8483ac2,0xb9303a17,0xbbf1afd6,0xbbb9b42c,0xb9fe394d,0xbaae3867,0xbb5ab64e,0xbad6b828,0xbc000000,0xbbf6ae46,0xb9a8b9a8,0xb913ba2f,
0xbbd9b23e,0xbba8b4a5,0xb872baa7,0xb78bbb0e,0xbb64b61f,0xbb0eb78b,0xb61fbb64,0xb4a5bba8,0xbaa7b872,0xba2fb913,0xb23ebbd9,0xae46bbf6,
0xbbf6ae46,0xbbd6b26f,0xb8c4ba6d,0xb812bae3,0xbba0b4d5,0xbb55b665,0xb6aabb46,0xb51dbb95,0xbaf6b7e3,0xba83b8a6,0xb303bbce,0xaf72bbf2,
0xb9feb94d,0xb969b9e5,0xa248bc00,0x2de2bbf7,0xbbd9b23e,0xbba0b4d5,0xb78bbb0e,0xb5f1bb6e,0xbb50b67c,0xbae9b807,0xb444bbb6,0xb115bbe6,
0xba6db8c4,0xb9dcb972,0xaa48bbfe,0x2bd9bbfc,0xb93aba0f,0xb887ba99,0x3179bbe2,0x3475bbaf,0xbba8b4a5,0xbb55b665,0xb564bb88,0xb334bbcb,
0xbae9b807,0xba65b8ce,0xaf0ebbf4,0x1e48bc00,0xb9cbb984,0xb91dba27,0x2fd6bbf1,0x3396bbc6,0xb85dbab5,0xb71bbb2b,0x3593bb80,0x3748bb20,
0xbb64b61f,0xbaf6b7e3,0xb23ebbd9,0xacb5bbfa,0xba6db8c4,0xb9cbb984,0x2a48bbfe,0x3179bbe2,0xb913ba2f,0xb848bac2,0x34a5bba8,0x367cbb50,
0xb6d7bb3b,0xb505bb99,0x381dbadd,0x38ecba4f,0xbb0eb78b,0xba83b8a6,0xaa48bbfe,0x2d1abbf9,0xb9dcb972,0xb91dba27,0x32a1bbd4,0x354cbb8c,
0xb848bac2,0xb6c1bb41,0x3732bb25,0x387cbaa0,0xb4d5bba0,0xb1aabbe0,0x394db9fe,0x3a07b943,0xbaa7b872,0xb9feb94d,0x2e46bbf6,0x3365bbc9,
0xb93aba0f,0xb85dbab5,0x35c2bb77,0x37b7bb02,0xb6d7bb3b,0xb4d5bba0,0x38c4ba6d,0x3996b9ba,0xb179bbe2,0xa8b6bbff,0x3a4fb8ec,0x3ae9b807,
0xba2fb913,0xb969b9e5,0x33c6bbc3,0x3608bb69,0xb887ba99,0xb71bbb2b,0x3807bae9,0x38f6ba47,0xb505bb99,0xb1aabbe0,0x39cbb984,0x3a83b8a6,
0xa8b6bbff,0x2eaabbf5,0x3b1ab75e,0x3b8cb54c,0x80003c00,0xb0b23bea,0xbb64361f,0xbbc333c6,0xb4a53ba8,0xb6d73b3b,0xbbf62e46,0xbbfeaa48,
0xb8723aa7,0xb95f39ed,0xbbd9b23e,0xbb88b564,0xba2f3913,0xbadd381d,0xbb0eb78b,0xba6db8c4,0x80003c00,0xb0e43be8,0xbb883564,0xbbdb320d,
0xb4d53ba0,0xb71b3b2b,0xbbff28b6,0xbbf2af72,0xb89b3a8a,0xb98d39c3,0xbbb6b444,0xbb4bb693,0xba5e38d8,0xbb0837a1,0xbab5b85d,0xb9f6b956,
0x80003c00,0xb1153be6,0xbba834a5,0xbbed304e,0xb5053b99,0xb75e3b1a,0xbbffa648,0xbbddb1db,0xb8c43a6d,0xb9ba3996,0xbb88b564,0xbb02b7b7,
0xba8a389b,0xbb303705,0xba4fb8ec,0xb972b9dc,0x80003c00,0xb1473be4,0xbbc333c6,0xbbf92d1a,0xb5343b91,0xb7a13b08,0xbbf8ad7e,0xbbc0b3f7,
0xb8ec3a4f,0xb9e53969,0xbb50b67c,0xbaaeb867,0xbab5385d,0xbb553665,0xb9dcb972,0xb8e2ba56,0x80003c00,0xb1793be2,0xbbd9323e,0xbbff2648,
0xb5643b88,0xb7e33af6,0xbbeab0b2,0xbb99b505,0xb9133a2f,0xba0f393a,0xbb0eb78b,0xba4fb8ec,0xbadd381d,0xbb7735c2,0xb95fb9ed,0xb848bac2,
0x80003c00,0xb1aa3be0,0xbbea30b2,0xbbffa7da,0xb5933b80,0xb8123ae3,0xbbd4b2a1,0xbb69b608,0xb93a3a0f,0xba373909,0xbac2b848,0xb9e5b969,
0xbb0237b7,0xbb95351d,0xb8d8ba5e,0xb748bb20,0x80003c00,0xb1db3bdd,0xbbf62e46,0xbbf8ad7e,0xb5c23b77,0xb8323ad0,0xbbb6b444,0xbb30b705,
0xb95f39ed,0xba5e38d8,0xba6db8c4,0xb972b9dc,0xbb253732,0xbbaf3475,0xb848bac2,0xb5f1bb6e,0x80003c00,0xb20d3bdb,0xbbfe2a48,0xbbecb080,
0xb5f13b6e,0xb8523abc,0xbb91b534,0xbaf0b7f9,0xb98439cb,0xba8338a6,0xba0fb93a,0xb8f6ba47,0xbb4636aa,0xbbc63396,0xb75ebb1a,0xb48dbbab,
0xb9a8b9a8,0xb8c4ba6d,0x361fbb64,0x381dbadd,0xb78bbb0e,0xb564bb88,0x3913ba2f,0x39edb95f,0xb23ebbd9,0xaa48bbfe,0x3aa7b872,0x3b3bb6d7,
0x2e46bbf6,0x33c6bbc3,0x3ba8b4a5,0x3beab0b2,0xb913ba2f,0xb812bae3,0x381dbadd,0x391dba27,0xb5f1bb6e,0xb334bbcb,0x39feb94d,0x3abcb852,
0xacb5bbfa,0x2d1abbf9,0x3b50b67c,0x3bb9b42c,0x3365bbc9,0x3608bb69,0x3bf4af0e,0x3bfe297f,0xb872baa7,0xb6aabb46,0x3913ba2f,0x39feb94d,
0xb444bbb6,0xaf0ebbf4,0x3ac2b848,0x3b5ab64e,0x2a48bbfe,0x32a1bbd4,0x3bc3b3c6,0x3bf8ad7e,0x35c2bb77,0x3807bae9,0x3bfa2cb5,0x3bc93365,
0xb78bbb0e,0xb51dbb95,0x39edb95f,0x3abcb852,0xb115bbe6,0x1e48bc00,0x3b5ab64e,0x3bc6b396,0x3179bbe2,0x354cbb8c,0x3bfaacb5,0x3bf72de2,
0x37b7bb02,0x38f6ba47,0x3bbc3414,0x3b4b3693,0xb61fbb64,0xb303bbce,0x3aa7b872,0x3b50b67c,0xaa48bbfe,0x2fd6bbf1,0x3bc3b3c6,0x3bfaacb5,
0x34a5bba8,0x3732bb25,0x3bf62e46,0x3bb63444,0x38c4ba6d,0x39cbb984,0x3b3b36d7,0x3a8a389b,0xb4a5bba8,0xaf72bbf2,0x3b3bb6d7,0x3bb9b42c,
0x2bd9bbfc,0x3396bbc6,0x3bf8ad7e,0x3bf72de2,0x367cbb50,0x387cbaa0,0x3bb63444,0x3b3636ee,0x3996b9ba,0x3a83b8a6,0x3a7c38b0,0x398d39c3,
0xb23ebbd9,0xa248bc00,0x3ba8b4a5,0x3bf4af0e,0x3179bbe2,0x3593bb80,0x3bfa2cb5,0x3bbc3414,0x381dbadd,0x394db9fe,0x3b3b36d7,0x3a7c38b0,
0x3a4fb8ec,0x3b1ab75e,0x398439cb,0x385d3ab5,0xae46bbf6,0x2de2bbf7,0x3beab0b2,0x3bfe297f,0x3475bbaf,0x3748bb20,0x3bc93365,0x3b4b3693,
0x38ecba4f,0x3a07b943,0x3a8a389b,0x398d39c3,0x3ae9b807,0x3b8cb54c,0x385d3ab5,0x36083b69,
};
__device__ __align__(1024) bf16 g_hT[2 * 1024 * 2048];
__device__ __align__(1024) bf16 g_U[128 * 2 * 8 * 1024];
__device__ __align__(16) float2 g_gate[2048];
__device__ __align__(16) uint4 g_agg[8 * 1024];
__device__ unsigned g_cnt[8 * 32];
constexpr int CNT_U = 0, CNT_V = 1, CNT_H = 2, CNT_DONE = 3, CNT_EPOCH = 4;
#define PROFK(i) do { } while (0)
#define PROF(i) do { } while (0)

constexpr int STAGE_BYTES = 49152;
constexpr int NSTAGE = 3;
constexpr int OFF_U = NSTAGE * STAGE_BYTES;
constexpr int OFF_W = OFF_U + 32768;
constexpr int OFF_GT = OFF_W + 32768;
constexpr int OFF_S = OFF_GT + 2048;
constexpr int OFF_F = OFF_W + 36864;
constexpr int OFF_TW = OFF_F + 8192;
constexpr int OFF_G = OFF_TW + 4096;
constexpr int OFF_BAR = OFF_G + 1024;
constexpr int OFF_GS = OFF_BAR + 128;
constexpr int SMEM_BYTES = OFF_GS + 128;
constexpr int BAR_FULL = 0, BAR_REL = 3  , BAR_X = 5, BAR_W = 6, BAR_U = 7, BAR_G1 = 8, BAR_C = 9, BAR_H = 10,
              BAR_CD = 11, BAR_E = 12, BAR_FREE = 13, BAR_P = 14, BAR_W2 = 15;

#define DEVI __device__ __forceinline__
constexpr unsigned SPIN_LIMIT = 1u << 27;

DEVI uint32_t smem_u32(const void* p) { return (uint32_t)__cvta_generic_to_shared(p); }
DEVI uint64_t gtime() { uint64_t t; asm volatile("mov.u64 %0, %%globaltimer;" : "=l"(t)); return t; }
DEVI void mbar_init(uint32_t bar, uint32_t cnt) { asm volatile("mbarrier.init.shared::cta.b64 [%0], %1;" :: "r"(bar), "r"(cnt) : "memory"); }
DEVI void mbar_expect_tx(uint32_t bar, uint32_t bytes) { asm volatile("mbarrier.arrive.expect_tx.shared::cta.b64 _, [%0], %1;" :: "r"(bar), "r"(bytes) : "memory"); }
DEVI void mbar_arrive(uint32_t bar) { asm volatile("mbarrier.arrive.shared::cta.b64 _, [%0];" :: "r"(bar) : "memory"); }
DEVI uint32_t mapa(uint32_t addr, uint32_t cta) { uint32_t r; asm volatile("mapa.shared::cluster.u32 %0, %1, %2;" : "=r"(r) : "r"(addr), "r"(cta)); return r; }
DEVI void mbar_arrive_remote(uint32_t rbar) { asm volatile("mbarrier.arrive.relaxed.cluster.shared::cluster.b64 _, [%0];" :: "r"(rbar) : "memory"); }
DEVI void mbar_wait(uint32_t bar, uint32_t parity) {
    asm volatile("{\n.reg .pred p;\n.reg .u32 n;\nmov.u32 n, 0;\n"
                 "LW:\nmbarrier.try_wait.parity.shared::cta.b64 p, [%0], %1;\n@p bra LD;\n"
                 "add.u32 n, n, 1;\nsetp.lt.u32 p, n, %2;\n@p bra LW;\ntrap;\nLD:\n}"
                 :: "r"(bar), "r"(parity), "n"(SPIN_LIMIT) : "memory");
}
DEVI void mbar_wait_cluster(uint32_t bar, uint32_t parity) {
    asm volatile("{\n.reg .pred p;\n.reg .u32 n;\nmov.u32 n, 0;\n"
                 "LW:\nmbarrier.try_wait.parity.acquire.cluster.shared::cta.b64 p, [%0], %1;\n@p bra LD;\n"
                 "add.u32 n, n, 1;\nsetp.lt.u32 p, n, %2;\n@p bra LW;\ntrap;\nLD:\n}"
                 :: "r"(bar), "r"(parity), "n"(SPIN_LIMIT) : "memory");
}
DEVI void cluster_arrive_relaxed() { asm volatile("barrier.cluster.arrive.relaxed.aligned;" ::: "memory"); }
DEVI void cluster_wait() { asm volatile("barrier.cluster.wait.aligned;" ::: "memory"); }
DEVI void fence_barrier_init() { asm volatile("fence.mbarrier_init.release.cluster;" ::: "memory"); }
DEVI void fence_proxy_async_smem() { asm volatile("fence.proxy.async.shared::cta;" ::: "memory"); }
DEVI void helper_sync() { asm volatile("bar.sync 1, 128;" ::: "memory"); }

DEVI void wait_counter(const unsigned* p, unsigned target) {
    for (unsigned n = 0;; n++) {
        unsigned v;
        asm volatile("ld.acquire.gpu.global.u32 %0, [%1];" : "=r"(v) : "l"(p) : "memory");
        if ((int)(v - target) >= 0) break;
        if (n > SPIN_LIMIT) __trap();
    }
}
DEVI void signal_counter(unsigned* p) {
    asm volatile("red.relaxed.gpu.global.add.u32 [%0], 1;" :: "l"(p) : "memory");
}

DEVI void tma_load_3d(uint32_t dst, const CUtensorMap* map, uint32_t bar, int c0, int c1, int c2) {
    asm volatile("cp.async.bulk.tensor.3d.shared::cluster.global.mbarrier::complete_tx::bytes [%0], [%1, {%3, %4, %5}], [%2];"
        :: "r"(dst), "l"(map), "r"(bar), "r"(c0), "r"(c1), "r"(c2) : "memory");
}
DEVI void tma_load_4d(uint32_t dst, const CUtensorMap* map, uint32_t bar, int c0, int c1, int c2, int c3) {
    asm volatile("cp.async.bulk.tensor.4d.shared::cluster.global.mbarrier::complete_tx::bytes [%0], [%1, {%3, %4, %5, %6}], [%2];"
        :: "r"(dst), "l"(map), "r"(bar), "r"(c0), "r"(c1), "r"(c2), "r"(c3) : "memory");
}
DEVI void tma_store_4d(const CUtensorMap* map, uint32_t src, int c0, int c1, int c2, int c3) {
    asm volatile("cp.async.bulk.tensor.4d.global.shared::cta.bulk_group [%0, {%2, %3, %4, %5}], [%1];"
        :: "l"(map), "r"(src), "r"(c0), "r"(c1), "r"(c2), "r"(c3) : "memory");
}
DEVI void bulk_load(uint32_t dst, const void* src, uint32_t bytes, uint32_t bar) {
    asm volatile("cp.async.bulk.shared::cluster.global.mbarrier::complete_tx::bytes [%0], [%1], %2, [%3];"
        :: "r"(dst), "l"(src), "r"(bytes), "r"(bar) : "memory");
}
DEVI void bulk_prefetch_l2(const void* src, uint32_t bytes) {
    asm volatile("cp.async.bulk.prefetch.L2.global [%0], %1;" :: "l"(src), "r"(bytes) : "memory");
}
DEVI void tma_store_3d(const CUtensorMap* map, uint32_t src, int c0, int c1, int c2) {
    asm volatile("cp.async.bulk.tensor.3d.global.shared::cta.bulk_group [%0, {%2, %3, %4}], [%1];"
        :: "l"(map), "r"(src), "r"(c0), "r"(c1), "r"(c2) : "memory");
}
DEVI void bulk_store(void* dst, uint32_t src, uint32_t bytes) {
    asm volatile("cp.async.bulk.global.shared::cta.bulk_group [%0], [%1], %2;" :: "l"(dst), "r"(src), "r"(bytes) : "memory");
}
DEVI void bulk_commit() { asm volatile("cp.async.bulk.commit_group;" ::: "memory"); }
DEVI void bulk_wait0() { asm volatile("cp.async.bulk.wait_group 0;" ::: "memory"); }

DEVI void wgmma_fence() { asm volatile("wgmma.fence.sync.aligned;" ::: "memory"); }
DEVI void wgmma_commit() { asm volatile("wgmma.commit_group.sync.aligned;" ::: "memory"); }
template<int N> DEVI void wgmma_wait() { asm volatile("wgmma.wait_group.sync.aligned %0;" :: "n"(N) : "memory"); }
template<int R> DEVI void reg_alloc() { asm volatile("setmaxnreg.inc.sync.aligned.u32 %0;" :: "n"(R)); }
template<int R> DEVI void reg_dealloc() { asm volatile("setmaxnreg.dec.sync.aligned.u32 %0;" :: "n"(R)); }

DEVI uint64_t make_desc(uint32_t addr, uint32_t lbo, uint32_t sbo, uint32_t mode = 1) {
    return (uint64_t)(((addr & 0x3FFFF) >> 4) | ((lbo >> 4) << 16)) | ((uint64_t)((sbo >> 4) | (mode << 30)) << 32);
}

#define ACC8(a, o) "+f"(a[o+0]), "+f"(a[o+1]), "+f"(a[o+2]), "+f"(a[o+3]), "+f"(a[o+4]), "+f"(a[o+5]), "+f"(a[o+6]), "+f"(a[o+7])
#define ACC32(a, o) ACC8(a, o), ACC8(a, o+8), ACC8(a, o+16), ACC8(a, o+24)

template<int TA, int TB>
DEVI void wgmma_n256(float (&d)[128], uint64_t da, uint64_t db, int scale_d) {
    asm volatile("{\n.reg .pred p;\nsetp.ne.b32 p, %130, 0;\n"
        "wgmma.mma_async.sync.aligned.m64n256k16.f32.bf16.bf16 "
        "{%0, %1, %2, %3, %4, %5, %6, %7, %8, %9, %10, %11, %12, %13, %14, %15, "
        "%16, %17, %18, %19, %20, %21, %22, %23, %24, %25, %26, %27, %28, %29, %30, %31, "
        "%32, %33, %34, %35, %36, %37, %38, %39, %40, %41, %42, %43, %44, %45, %46, %47, "
        "%48, %49, %50, %51, %52, %53, %54, %55, %56, %57, %58, %59, %60, %61, %62, %63, "
        "%64, %65, %66, %67, %68, %69, %70, %71, %72, %73, %74, %75, %76, %77, %78, %79, "
        "%80, %81, %82, %83, %84, %85, %86, %87, %88, %89, %90, %91, %92, %93, %94, %95, "
        "%96, %97, %98, %99, %100, %101, %102, %103, %104, %105, %106, %107, %108, %109, %110, %111, "
        "%112, %113, %114, %115, %116, %117, %118, %119, %120, %121, %122, %123, %124, %125, %126, %127}, "
        "%128, %129, p, 1, 1, %131, %132;\n}\n"
        : ACC32(d, 0), ACC32(d, 32), ACC32(d, 64), ACC32(d, 96)
        : "l"(da), "l"(db), "r"(scale_d), "n"(TA), "n"(TB));
}
template<int SCALE_D>
DEVI void wgmma_n128(float (&d)[64], uint64_t da, uint64_t db) {
    asm volatile("{\n.reg .pred p;\nsetp.ne.b32 p, %66, 0;\n"
        "wgmma.mma_async.sync.aligned.m64n128k16.f32.bf16.bf16 "
        "{%0, %1, %2, %3, %4, %5, %6, %7, %8, %9, %10, %11, %12, %13, %14, %15, "
        "%16, %17, %18, %19, %20, %21, %22, %23, %24, %25, %26, %27, %28, %29, %30, %31, "
        "%32, %33, %34, %35, %36, %37, %38, %39, %40, %41, %42, %43, %44, %45, %46, %47, "
        "%48, %49, %50, %51, %52, %53, %54, %55, %56, %57, %58, %59, %60, %61, %62, %63}, "
        "%64, %65, p, 1, 1, 0, 1;\n}\n"
        : ACC32(d, 0), ACC32(d, 32)
        : "l"(da), "l"(db), "n"(SCALE_D));
}
template<int SCALE_D>
DEVI void wgmma_n64(float (&d)[32], uint64_t da, uint64_t db) {
    asm volatile("{\n.reg .pred p;\nsetp.ne.b32 p, %34, 0;\n"
        "wgmma.mma_async.sync.aligned.m64n64k16.f32.bf16.bf16 "
        "{%0, %1, %2, %3, %4, %5, %6, %7, %8, %9, %10, %11, %12, %13, %14, %15, "
        "%16, %17, %18, %19, %20, %21, %22, %23, %24, %25, %26, %27, %28, %29, %30, %31}, "
        "%32, %33, p, 1, 1, 1, 1;\n}\n"
        : ACC32(d, 0)
        : "l"(da), "l"(db), "n"(SCALE_D));
}
DEVI void wgmma_n16(float (&d)[8], uint64_t da, uint64_t db) {
    asm volatile("{\n.reg .pred p;\nsetp.ne.b32 p, 0, 0;\n"
        "wgmma.mma_async.sync.aligned.m64n16k16.f32.bf16.bf16 "
        "{%0, %1, %2, %3, %4, %5, %6, %7}, %8, %9, p, 1, 1, 1, 0;\n}\n"
        : ACC8(d, 0)
        : "l"(da), "l"(db));
}
template<int SCALE_D>
DEVI void wgmma_rs_n64(float (&d)[32], const uint32_t (&a)[4], uint64_t db) {
    asm volatile("{\n.reg .pred p;\nsetp.ne.b32 p, %37, 0;\n"
        "wgmma.mma_async.sync.aligned.m64n64k16.f32.bf16.bf16 "
        "{%0, %1, %2, %3, %4, %5, %6, %7, %8, %9, %10, %11, %12, %13, %14, %15, "
        "%16, %17, %18, %19, %20, %21, %22, %23, %24, %25, %26, %27, %28, %29, %30, %31}, "
        "{%32, %33, %34, %35}, %36, p, 1, 1, 0;\n}\n"
        : ACC32(d, 0)
        : "r"(a[0]), "r"(a[1]), "r"(a[2]), "r"(a[3]), "l"(db), "n"(SCALE_D));
}
DEVI void ldsm_x4(uint32_t (&r)[4], uint32_t addr) {
    asm volatile("ldmatrix.sync.aligned.m8n8.x4.shared.b16 {%0, %1, %2, %3}, [%4];"
        : "=r"(r[0]), "=r"(r[1]), "=r"(r[2]), "=r"(r[3]) : "r"(addr) : "memory");
}
DEVI void ldsm_x4_t(uint32_t (&r)[4], uint32_t addr) {
    asm volatile("ldmatrix.sync.aligned.m8n8.x4.trans.shared.b16 {%0, %1, %2, %3}, [%4];"
        : "=r"(r[0]), "=r"(r[1]), "=r"(r[2]), "=r"(r[3]) : "r"(addr) : "memory");
}
DEVI void stsm_x4(uint32_t addr, uint32_t r0, uint32_t r1, uint32_t r2, uint32_t r3) {
    asm volatile("stmatrix.sync.aligned.m8n8.x4.shared.b16 [%0], {%1, %2, %3, %4};"
        :: "r"(addr), "r"(r0), "r"(r1), "r"(r2), "r"(r3) : "memory");
}
DEVI void stsm_x4_t(uint32_t addr, uint32_t r0, uint32_t r1, uint32_t r2, uint32_t r3) {
    asm volatile("stmatrix.sync.aligned.m8n8.x4.trans.shared.b16 [%0], {%1, %2, %3, %4};"
        :: "r"(addr), "r"(r0), "r"(r1), "r"(r2), "r"(r3) : "memory");
}
DEVI uint32_t movm(uint32_t a) { uint32_t d; asm volatile("movmatrix.sync.aligned.m8n8.trans.b16 %0, %1;" : "=r"(d) : "r"(a)); return d; }
DEVI uint32_t pack2(float lo, float hi) { uint32_t d; asm("cvt.rn.bf16x2.f32 %0, %1, %2;" : "=r"(d) : "f"(hi), "f"(lo)); return d; }
DEVI float bf_lo(uint32_t v) { return __uint_as_float(v << 16); }
DEVI float bf_hi(uint32_t v) { return __uint_as_float(v & 0xffff0000u); }
DEVI float bf_round(float v) { return __bfloat162float(__float2bfloat16_rn(v)); }
DEVI uint32_t bf_mul2(uint32_t a, uint32_t b) { uint32_t d; asm("mul.rn.bf16x2 %0, %1, %2;" : "=r"(d) : "r"(a), "r"(b)); return d; }
DEVI float4 lds128(uint32_t a) { float4 v; asm volatile("ld.shared.v4.f32 {%0, %1, %2, %3}, [%4];" : "=f"(v.x), "=f"(v.y), "=f"(v.z), "=f"(v.w) : "r"(a) : "memory"); return v; }
DEVI uint4 lds128u(uint32_t a) { uint4 v; asm volatile("ld.shared.v4.u32 {%0, %1, %2, %3}, [%4];" : "=r"(v.x), "=r"(v.y), "=r"(v.z), "=r"(v.w) : "r"(a) : "memory"); return v; }
DEVI void sts128(uint32_t a, float x, float y, float z, float w) { asm volatile("st.shared.v4.f32 [%0], {%1, %2, %3, %4};" :: "r"(a), "f"(x), "f"(y), "f"(z), "f"(w) : "memory"); }
DEVI void sts128u(uint32_t a, uint32_t x, uint32_t y, uint32_t z, uint32_t w) { asm volatile("st.shared.v4.u32 [%0], {%1, %2, %3, %4};" :: "r"(a), "r"(x), "r"(y), "r"(z), "r"(w) : "memory"); }
DEVI uint32_t lds16(uint32_t a) { uint32_t v; asm volatile("ld.shared.u16 %0, [%1];" : "=r"(v) : "r"(a) : "memory"); return v; }
DEVI void sts16(uint32_t a, float v) { asm volatile("st.shared.u16 [%0], %1;" :: "r"(a), "r"(pack2(v, v)) : "memory"); }

DEVI float2 cmul(float2 a, float2 b) { return make_float2(fmaf(a.x, b.x, -a.y * b.y), fmaf(a.x, b.y, a.y * b.x)); }
DEVI float2 cfma(float2 a, float2 b, float2 c) { return make_float2(fmaf(a.x, b.x, fmaf(-a.y, b.y, c.x)), fmaf(a.x, b.y, fmaf(a.y, b.x, c.y))); }
DEVI float2 cadd(float2 a, float2 b) { return make_float2(a.x + b.x, a.y + b.y); }
DEVI float2 csub(float2 a, float2 b) { return make_float2(a.x - b.x, a.y - b.y); }
DEVI void fft4(float2& a, float2& b, float2& c, float2& d) {
    const float2 s0 = cadd(a, c), s1 = csub(a, c), s2 = cadd(b, d), t = csub(b, d), s3 = make_float2(t.y, -t.x);
    a = cadd(s0, s2); b = cadd(s1, s3); c = csub(s0, s2); d = csub(s1, s3);
}
DEVI float2 h2f(uint32_t v) { return __half22float2(*(const __half2*)&v); }

struct Params {
    const bf16 *x, *lam_re, *lam_im, *log_dt, *dskip, *gate_w, *c_re, *c_im, *b_re, *b_im, *w_r, *w_i;
    float* out;
    int swapB;
};

DEVI void pace(uint32_t cnt_addr) {
    uint32_t v0, v;
    asm volatile("ld.volatile.shared.u32 %0, [%1];" : "=r"(v0) : "r"(cnt_addr) : "memory");
    const unsigned t0 = clock();
    do {
        __nanosleep(20);
        asm volatile("ld.volatile.shared.u32 %0, [%1];" : "=r"(v) : "r"(cnt_addr) : "memory");
    } while (v == v0 && clock() - t0 < 1300u);
}

DEVI void helper_radix8(uint32_t sb, uint32_t gtab, int w, int lane) {
    const uint64_t dg = make_desc(gtab, 128, 256, 0);
    const uint32_t st = sb + OFF_U + (lane >> 4) * 16384 + (lane & 7) * 128 + (((2 * w + ((lane >> 3) & 1)) ^ (lane & 7)) << 4);
#pragma unroll 1
    for (int hf = 0; hf < 2; hf++) {
        float acc[8][8];
        const uint64_t da = make_desc(sb + OFF_U + hf * 8192, 16, 16384);
        wgmma_fence();
#pragma unroll
        for (int i = 0; i < 8; i++) wgmma_n16(acc[i], da + 64 * i, dg);
        wgmma_commit();
        wgmma_wait<0>();
        helper_sync();
#pragma unroll
        for (int i = 0; i < 8; i++)
            stsm_x4_t((st ^ ((i & 3) << 4)) + hf * 8192 + i * 1024,
                      pack2(acc[i][0], acc[i][1]), pack2(acc[i][2], acc[i][3]), pack2(acc[i][4], acc[i][5]), pack2(acc[i][6], acc[i][7]));
    }
}
DEVI uint32_t swz(uint32_t a) { return a ^ ((a >> 3) & 0x70); }

DEVI void c_mm(float (&acc)[2][32], const uint32_t (&a)[2][4][4], uint64_t df) {
    wgmma_fence();
#pragma unroll
    for (int h = 0; h < 2; h++) {
        wgmma_rs_n64<0>(acc[h], a[h][0], df);
        wgmma_rs_n64<1>(acc[h], a[h][1], df + 2);
        wgmma_rs_n64<1>(acc[h], a[h][2], df + 4);
        wgmma_rs_n64<1>(acc[h], a[h][3], df + 6);
    }
    wgmma_commit();
    wgmma_wait<0>();
}

DEVI void phase_c(uint32_t sb, int mrow, int warp, int lane) {
    const uint64_t df = make_desc(sb + OFF_F, 16, 1024);
    const uint32_t tw_addr = sb + OFF_TW + lane * 16;
    uint32_t a[2][4][4];
    float acc[2][32];
    const uint32_t xa = sb + OFF_U + ((lane >> 4) * 4 + ((lane & 7) >> 1)) * 1024 + warp * 128
                      + ((((lane & 1) * 4 + ((lane >> 3) & 1)) ^ warp ^ ((lane >> 1) & 3)) << 4);
#pragma unroll
    for (int h = 0; h < 2; h++)
#pragma unroll
        for (int s = 0; s < 4; s++) ldsm_x4_t(a[h][s], (xa ^ (h * 32)) + (s & 1) * 8192 + (s >> 1) * 16384);
#pragma unroll 1
    for (int rep = 0; rep < 2; rep++) {
        c_mm(acc, a, df);
#pragma unroll
        for (int h = 0; h < 2; h++)
#pragma unroll
            for (int hh = 0; hh < 2; hh++)
#pragma unroll
                for (int jp = 0; jp < 2; jp++) {
                    const uint4 w = lds128u(tw_addr + ((h * 2 + hh) * 2 + jp) * 512);
#pragma unroll
                    for (int jl = 0; jl < 2; jl++) {
                        const int o = 8 * jp + 4 * jl + 2 * hh;
                        const float2 v0 = cmul(make_float2(acc[h][o], acc[h][16 + o]), h2f(jl ? w.z : w.x));
                        const float2 v1 = cmul(make_float2(acc[h][o + 1], acc[h][17 + o]), h2f(jl ? w.w : w.y));
                        a[jp][h][2 * hh + jl] = movm(pack2(v0.x, v1.x));
                        a[jp][2 + h][2 * hh + jl] = movm(pack2(v0.y, v1.y));
                    }
                }
        c_mm(acc, a, df);
        if (rep == 0) {
            const uint32_t w0 = sb + OFF_W + warp * 1152 + lane * 16, w1 = sb + OFF_W + 9216 + mrow * 1152 + lane * 16;
#pragma unroll
            for (int h = 0; h < 2; h++)
#pragma unroll
                for (int j = 0; j < 4; j++) {
                    const uint4 w = lds128u(((j >> 1) ? w1 : w0) + h * 18432 + (j & 1) * 512);
#pragma unroll
                    for (int hh = 0; hh < 2; hh++) {
                        const int o = 4 * j + 2 * hh;
                        const uint32_t u0 = hh ? w.z : w.x, u1 = hh ? w.w : w.y;
                        const float2 r0 = cmul(make_float2(acc[h][o], acc[h][16 + o]), make_float2(bf_lo(u0), bf_hi(u0)));
                        const float2 r1 = cmul(make_float2(acc[h][o + 1], acc[h][17 + o]), make_float2(bf_lo(u1), bf_hi(u1)));
                        a[h][j >> 1][2 * (j & 1) + hh] = pack2(r0.y, r1.y);
                        a[h][2 + (j >> 1)][2 * (j & 1) + hh] = pack2(r0.x, r1.x);
                    }
                }
        }
    }
#pragma unroll
    for (int h = 0; h < 2; h++)
#pragma unroll
        for (int s = 0; s < 4; s++) {
            const float* v = &acc[h][8 * s];
            stsm_x4_t((xa ^ (h * 32)) + (s & 1) * 8192 + ((s >> 1) ^ 1) * 16384,
                      pack2(v[0], v[1]), pack2(v[2], v[3]), pack2(v[4], v[5]), pack2(v[6], v[7]));
        }
}

__global__ void __cluster_dims__(2, 1, 1) __launch_bounds__(384, 1)
fused_kernel(const __grid_constant__ CUtensorMap mapB, const __grid_constant__ CUtensorMap mapX,
             const __grid_constant__ CUtensorMap mapH, const __grid_constant__ CUtensorMap mapCre,
             const __grid_constant__ CUtensorMap mapCim, const __grid_constant__ CUtensorMap mapXs,
             const __grid_constant__ CUtensorMap mapU1, const __grid_constant__ CUtensorMap mapU2,
             const __grid_constant__ CUtensorMap mapWr, const __grid_constant__ CUtensorMap mapWi,
             const __grid_constant__ CUtensorMap mapH2,
             const __grid_constant__ Params P) {
    extern __shared__ __align__(1024) uint8_t sm[];
    const uint32_t sb = smem_u32(sm);
    const uint32_t bars = sb + OFF_BAR;
    const int b = blockIdx.x, tid = threadIdx.x, warp = tid >> 5, lane = tid & 31;
    const bool main_cta = b < 128;
    if (b == 129) return;

    auto issue_loads = [&](int it, int s) {
        const uint32_t full = bars + 8 * (BAR_FULL + s), st = sb + s * STAGE_BYTES;
        mbar_expect_tx(full, STAGE_BYTES);
        if (it < 16) {
            tma_load_4d(st, &mapB, full, it * 64, 0, 0, (b & 15) * 8);
            tma_load_4d(st + 16384, &mapX, full, it * 64, 0, 0, (b >> 4) * 128);
        } else {
            const int k = it - 16;
            tma_load_4d(st, (b & 1) ? &mapCim : &mapCre, full, k * 64, 0, 0, (b & 14) * 8);
            if (k >= NSTAGE) tma_load_3d(st + 16384, &mapH, full, 0, (b & 1) * 1024 + k * 64, (b >> 4) * 4);
        }
    };
    auto load_x_tile = [&](bool paced) {
        const uint32_t bx = bars + 8 * BAR_X;
        mbar_expect_tx(bx, 32768 + 8192);
#pragma unroll 1
        for (int i = 0; i < 2; i++) {
            if (paced) pace(bars + 8 * BAR_REL + 12);
            tma_load_4d(sb + OFF_W + i * 16384, &mapXs, bx, (b & 15) * 64 + i * 32, 0, 0, b >> 4);
        }
        if (paced) pace(bars + 8 * BAR_REL + 12);
        bulk_load(sb + OFF_F, c_tab, 8192, bx);
    };

    if (tid == 256) {
        PROF(0);
        if (sb & 1023) __trap();
#pragma unroll
        for (int i = 0; i < 16; i++) {
            const int cnt = i == BAR_G1 ? 2 : (i == BAR_H || i == BAR_CD) ? 256 : (i == BAR_E || i == BAR_C) ? 128 : 1;
            if (i == 3 || i == 4) *(uint64_t*)(sm + OFF_BAR + 8 * i) = 0; else mbar_init(bars + 8 * i, cnt);
        }
        fence_barrier_init();
        fence_proxy_async_smem();
    } else if (warp == 9 && lane < 11) {
        asm volatile("prefetch.tensormap [%0];" :: "l"(&mapB + lane) : "memory");
    }
    const int pp = (b & 15) * 64 + ((tid >> 2) & 63);
    const bf16 lr_ = P.lam_re[pp], li_ = P.lam_im[pp], ld_ = P.log_dt[pp];
    unsigned epoch;
    asm volatile("ld.volatile.global.u32 %0, [%1];" : "=r"(epoch) : "l"(&g_cnt[CNT_EPOCH * 32]));
    __syncthreads();
    if (tid == 256 && main_cta) {
        PROF(28);
#pragma unroll 1
        for (int it = 0; it < NSTAGE; it++) issue_loads(it, it);
        PROF(27);
        load_x_tile(false);
        mbar_expect_tx(bars + 8 * BAR_P, 65536);
    }
    __syncwarp();
    if (main_cta) cluster_arrive_relaxed();
    epoch += 1;
    const int cls = b == 128 ? 128 : (b & 31) ? (b & 31) + 64 * (b >> 5) : (b == 64 ? 32 : b == 32 ? 64 : b);
    const int g = lane >> 2, q = lane & 3;

    if (warp < 8) {
        reg_alloc<200>();
        const int wg = warp >> 2;
        const bool leader = (tid & 127) == 0;
        int s = 0; uint32_t ph = 0;
        auto release = [&](int it, int sp) {
            if (leader) {
                unsigned old;
                asm volatile("atom.relaxed.cta.shared.inc.u32 %0, [%1], 1;" : "=r"(old) : "r"(bars + 8 * BAR_REL + 4 * sp) : "memory");
                if (old == 1) {
                    if (it + NSTAGE < 32) issue_loads(it + NSTAGE, sp);
                    else if (it == 30) mbar_arrive_remote(mapa(bars + 8 * BAR_FREE, (b & 1) ^ 1));
                    asm volatile("st.volatile.shared.u32 [%0], %1;" :: "r"(bars + 8 * BAR_REL + 12), "r"(it + 1) : "memory");
                    if (it < 4) bulk_prefetch_l2(((it & 1) ? P.w_i : P.w_r) + (size_t)(2 * b + (it >> 1)) * 4104, 8208);
                    else if (it < 12) bulk_prefetch_l2(((b & 1) ? P.c_im : P.c_re) + (size_t)(b >> 1) * 16384 + (it - 4) * 2048, 4096);
                }
            }
            __syncwarp();
        };
        if (main_cta) {
            float acc[128];
            const int pt = b & 15, tc = b >> 4;
            const int p = pt * 64 + warp * 8 + g;
            float2 lam1, lam32, lam64, lam128, wq, w4, l64q, coef;
            {
                const float lr = __bfloat162float(lr_), li = __bfloat162float(li_);
                const float dt = bf_round(expf(__bfloat162float(ld_)));
                const float mag = expf(dt * lr);
                float sn, cs; sincosf(dt * li, &sn, &cs);
                lam1 = make_float2(mag * cs, mag * sn);
                const float inv = 1.f / (lr * lr + li * li);
                coef = cmul(make_float2(lam1.x - 1.f, lam1.y), make_float2(lr * inv, -li * inv));
                if (P.swapB) { lam1.y = -lam1.y; coef.y = -coef.y; }
                float2 z = lam1;
#pragma unroll
                for (int i = 0; i < 5; i++) z = cmul(z, z);
                lam32 = z; lam64 = cmul(z, z); lam128 = cmul(lam64, lam64);
                const float2 l256 = cmul(lam128, lam128), l512 = cmul(l256, l256);
                w4 = cmul(l512, l512);
                const float2 one = make_float2(1.f, 0.f);
                wq = cmul((q & 1) ? l256 : one, (q & 2) ? l512 : one);
                l64q = cmul((q & 1) ? lam64 : one, (q & 2) ? lam128 : one);
            }
            const int gn = 16 * pt + 2 * warp + (lane >> 4);
            const uint32_t goff = 16384 + gn * 128 + ((((lane & 15) >> 1) ^ (gn & 7)) << 4) + (lane & 1) * 8;
            const uint2* gwp = (const uint2*)P.gate_w + (lane & 15);
            uint2 gw = __ldg(gwp);
            float gs = 0.f;
#pragma unroll 1
            for (int it = 0; it < 16; it++) {
                mbar_wait(bars + 8 * (BAR_FULL + s), ph);
                if (it == 0 && tid == 0) PROF(2);
                if (tid == 0) PROFK(it);
                const uint32_t st = sb + s * STAGE_BYTES;
                const uint64_t da = make_desc(st + wg * 8192, 16, 1024), db = make_desc(st + 16384, 16, 1024);
                {
                    uint32_t x0, x1;
                    asm volatile("ld.shared.v2.u32 {%0, %1}, [%2];" : "=r"(x0), "=r"(x1) : "r"(st + goff) : "memory");
                    x0 = bf_mul2(x0, gw.x); x1 = bf_mul2(x1, gw.y);
                    asm volatile("" : "+r"(x0), "+r"(x1) :: "memory");
                    gs += (bf_lo(x0) + bf_hi(x0)) + (bf_lo(x1) + bf_hi(x1));
                    gw = __ldg(gwp + ((it + 1) & 15) * 16);
                }
                wgmma_fence();
#pragma unroll
                for (int j = 0; j < 4; j++) wgmma_n256<0, 0>(acc, da + 2 * j, db + 2 * j, (it | j) != 0);
                wgmma_commit();
                if (it > 0) {
                    wgmma_wait<1>();
                    release(it - 1, s == 0 ? 2 : s - 1);
                }
                if (++s == NSTAGE) { s = 0; ph ^= 1; }
            }
#pragma unroll
            for (int o = 1; o < 16; o <<= 1) gs += __shfl_xor_sync(0xffffffffu, gs, o);
            {
                const float gg = bf_round(__fdividef(1.f, 1.f + __expf(-bf_round(gs))));
                if ((lane & 15) == 0) *(float2*)(sm + OFF_GS + (2 * warp + (lane >> 4)) * 8) = make_float2(gg, bf_round(1.f - gg));
            }
            wgmma_wait<0>();
            if (leader) mbar_arrive(bars + 8 * BAR_G1);
            release(15, 0);
            if (tid == 0) PROF(3);
            float2 lo = make_float2(acc[0], acc[2]), hi = make_float2(acc[64], acc[66]);
#pragma unroll
            for (int t = 1; t < 32; t++) {
                const int i = 4 * (t >> 1) + (t & 1);
                lo = cfma(lam1, lo, make_float2(acc[i], acc[i + 2]));
                hi = cfma(lam1, hi, make_float2(acc[64 + i], acc[66 + i]));
            }
            float2 v = cfma(lam32, lo, hi);
            {
                float2 n = make_float2(__shfl_up_sync(0xffffffffu, v.x, 1, 4), __shfl_up_sync(0xffffffffu, v.y, 1, 4));
                if (q >= 1) v = cfma(lam64, n, v);
                n = make_float2(__shfl_up_sync(0xffffffffu, v.x, 2, 4), __shfl_up_sync(0xffffffffu, v.y, 2, 4));
                if (q >= 2) v = cfma(lam128, n, v);
            }
            if (q == 3 && tc < 7) {
                asm volatile("st.volatile.global.v4.u32 [%0], {%1, %2, %3, %4};"
                    :: "l"(&g_agg[tc * 1024 + p]), "r"(__float_as_uint(v.x)), "r"(epoch), "r"(__float_as_uint(v.y)), "r"(epoch) : "memory");
            }
            float2 ex = make_float2(__shfl_up_sync(0xffffffffu, v.x, 1, 4), __shfl_up_sync(0xffffffffu, v.y, 1, 4));
            if (q == 0) ex = make_float2(0.f, 0.f);
#pragma unroll
            for (int i = 0; i < 128; i += 4) {
                const float2 u0 = cmul(coef, make_float2(acc[i], acc[i + 2])), u1 = cmul(coef, make_float2(acc[i + 1], acc[i + 3]));
                acc[i] = u0.x; acc[i + 2] = u0.y; acc[i + 1] = u1.x; acc[i + 3] = u1.y;
            }
            {
                float2 part = make_float2(0.f, 0.f);
                const int c0 = tc - 1 - q, c1 = tc - 5 - q;
                if (c0 >= 0) {
                    uint4 r0, r1 = make_uint4(0, epoch, 0, epoch);
                    for (unsigned n = 0;; n++) {
                        asm volatile("ld.volatile.global.v4.u32 {%0, %1, %2, %3}, [%4];" : "=r"(r0.x), "=r"(r0.y), "=r"(r0.z), "=r"(r0.w) : "l"(&g_agg[c0 * 1024 + p]) : "memory");
                        if (c1 >= 0) asm volatile("ld.volatile.global.v4.u32 {%0, %1, %2, %3}, [%4];" : "=r"(r1.x), "=r"(r1.y), "=r"(r1.z), "=r"(r1.w) : "l"(&g_agg[c1 * 1024 + p]) : "memory");
                        if (r0.y == epoch && r0.w == epoch && r1.y == epoch && r1.w == epoch) break;
                        if (n > SPIN_LIMIT) __trap();
                    }
                    part = cfma(w4, make_float2(__uint_as_float(r1.x), __uint_as_float(r1.z)), make_float2(__uint_as_float(r0.x), __uint_as_float(r0.z)));
                    part = cmul(wq, part);
                }
                __syncwarp();
                part.x += __shfl_xor_sync(0xffffffffu, part.x, 1); part.y += __shfl_xor_sync(0xffffffffu, part.y, 1);
                part.x += __shfl_xor_sync(0xffffffffu, part.x, 2); part.y += __shfl_xor_sync(0xffffffffu, part.y, 2);
                ex = cfma(l64q, part, ex);
            }
            if (tid == 0) PROF(4);
            float2 h0 = cmul(coef, ex), h1 = cmul(coef, cfma(lam32, ex, lo));
            {
                mbar_wait(bars + 8 * BAR_G1, 0);
                const uint32_t hs = sb + STAGE_BYTES + 16384 + tid * 16;
                uint32_t hr[32], hi2[32];
#pragma unroll
                for (int t = 0; t < 32; t++) {
                    const int i = 4 * (t >> 1) + (t & 1);
                    h0 = cfma(lam1, h0, make_float2(acc[i], acc[i + 2]));
                    h1 = cfma(lam1, h1, make_float2(acc[64 + i], acc[66 + i]));
                    hr[t] = pack2(h0.x, h1.x); hi2[t] = pack2(h0.y, h1.y);
                    if (t >= 24) {
                        const int r = t - 24;
                        sts128u(hs + r * 4096, hr[r], hr[r + 8], hr[r + 16], hr[r + 24]);
                        sts128u(hs + STAGE_BYTES + r * 4096, hi2[r], hi2[r + 8], hi2[r + 16], hi2[r + 24]);
                    }
                }
            }
            fence_proxy_async_smem();
            mbar_arrive(bars + 8 * BAR_H);
            if (tid == 0) PROF(5);
            cluster_wait();
        }
        mbar_wait(bars + 8 * BAR_C, 0);
        if (tid == 0) PROF(6);
        phase_c(sb, b == 0 ? (8 - warp) & 7 : 7 - warp, warp, lane);
        fence_proxy_async_smem();
        mbar_arrive(bars + 8 * BAR_CD);
        if (tid == 0) PROF(7);
        if (main_cta) {
            float acc[128];
            const int ks = b & 1;
#pragma unroll 1
            for (int it = 16; it < 32; it++) {
                mbar_wait(bars + 8 * (BAR_FULL + s), ph);
                if (it == 16 && tid == 0) PROF(16);
                if (tid == 0) PROFK(it);
                const uint32_t st = sb + s * STAGE_BYTES;
                const uint64_t da = make_desc(st + wg * 8192, 16, 1024), db = make_desc(st + 16384, 8192, 1024);
                wgmma_fence();
#pragma unroll
                for (int j = 0; j < 4; j++) wgmma_n256<0, 1>(acc, da + 2 * j, db + 128 * j, it + j != 16);
                wgmma_commit();
                if (it > 16) {
                    wgmma_wait<1>();
                    release(it - 1, s == 0 ? 2 : s - 1);
                }
                if (++s == NSTAGE) { s = 0; ph ^= 1; }
            }
            wgmma_wait<0>();
            if (tid == 0) PROF(17);
            mbar_wait_cluster(bars + 8 * BAR_FREE, 0);
            {
                const uint32_t rbar = mapa(bars + 8 * BAR_P, ks ^ 1);
                const uint32_t r0 = mapa(sb + tid * 16, ks ^ 1);
#pragma unroll
                for (int u = 0; u < 16; u++) {
                    const int i0 = 4 * (8 * (u >> 2) + (u & 3)), i1 = i0 + 16;
                    asm volatile("st.async.weak.shared::cluster.mbarrier::complete_tx::bytes.v4.f32 [%0], {%1, %2, %3, %4}, [%5];"
                        :: "r"(r0 + (u < 12 ? 2 * STAGE_BYTES + u * 4096 : (u - 12) * 4096)),
                           "f"(ks ? acc[i0] : acc[i0 + 2]), "f"(ks ? acc[i0 + 1] : acc[i0 + 3]),
                           "f"(ks ? acc[i1] : acc[i1 + 2]), "f"(ks ? acc[i1 + 1] : acc[i1 + 3]), "r"(rbar) : "memory");
                }
            }
            mbar_wait(bars + 8 * BAR_E, 0);
            float sc[64];
#pragma unroll
            for (int i = 0; i < 16; i++) {
                const float4 v = lds128(sb + OFF_S + q * 272 + i * 16);
                sc[4 * i] = v.x; sc[4 * i + 1] = v.y; sc[4 * i + 2] = v.z; sc[4 * i + 3] = v.w;
            }
            const uint32_t ea = sb + ((warp & 1) ? OFF_W : OFF_U) + (warp >> 2) * 16384 + ((warp >> 1) & 1) * 2048 + q * 4096 + g * 64 + q * 16;
#pragma unroll
            for (int u = 0; u < 16; u++) {
                const int J = 8 * (u >> 2) + (u & 3), i0 = 4 * J, i1 = i0 + 16;
                const float4 e = lds128((ea ^ ((u & 3) << 4)) + (u >> 2) * 512);
                acc[i0] = fmaf(sc[2 * J], ks ? acc[i0 + 2] : acc[i0], e.x); acc[i0 + 1] = fmaf(sc[2 * J + 1], ks ? acc[i0 + 3] : acc[i0 + 1], e.y);
                acc[i1] = fmaf(sc[2 * J + 8], ks ? acc[i1 + 2] : acc[i1], e.z); acc[i1 + 1] = fmaf(sc[2 * J + 9], ks ? acc[i1 + 3] : acc[i1 + 1], e.w);
            }
            mbar_wait_cluster(bars + 8 * BAR_P, 0);
            if (tid == 0) PROF(18);
            float* o = P.out + (size_t)((b >> 4) + 8 * q) * 1024 + (b & 15) * 64 + warp * 8 + g;
#pragma unroll
            for (int u = 0; u < 16; u++) {
                const int J = 8 * (u >> 2) + (u & 3), i0 = 4 * J, i1 = i0 + 16;
                const float4 r = lds128(sb + (u < 12 ? 2 * STAGE_BYTES + u * 4096 : (u - 12) * 4096) + tid * 16);
                o[(64 * J) * 1024] = fmaf(-sc[2 * J], r.x, acc[i0]);
                o[(64 * J + 32) * 1024] = fmaf(-sc[2 * J + 1], r.y, acc[i0 + 1]);
                o[(64 * J + 256) * 1024] = fmaf(-sc[2 * J + 8], r.z, acc[i1]);
                o[(64 * J + 288) * 1024] = fmaf(-sc[2 * J + 9], r.w, acc[i1 + 1]);
            }
            if (tid == 0) PROF(19);
        }
        if (tid == 0) {
            const unsigned old = atomicAdd(&g_cnt[CNT_DONE * 32], 1u);
            if (old == 128) { g_cnt[CNT_DONE * 32] = 0; g_cnt[CNT_EPOCH * 32] = epoch; }
        }
    } else {
        reg_dealloc<104>();
        const int t = tid - 256, w = warp - 8;
        const bool real_cls = (cls & 127) == 0;
        const bool special = t < 4;
        const uint32_t prog = bars + 8 * BAR_REL + 12;
        const float R = 0.70710678118654752f;
        float2 w1, w2, w3;
        {
            const int kk = (t >> 3) & 7, r = t & 7;
            float sn, cs;
            sincospif((float)(((cls + 256 * kk) * r) & 2047) * (1.f / 1024.f), &sn, &cs);
            sn *= 1.f / 1024.f; cs *= 1.f / 1024.f;
            const uint32_t gf = sb + OFF_G + kk * 16 + r * 2, gi = sb + OFF_G + 512 + r * 16 + kk * 2;
            if (t < 64) {
                sts16(gf, cs); sts16(gf + 128, real_cls ? 0.f : sn); sts16(gf + 256, -sn); sts16(gf + 384, real_cls ? 0.f : cs);
                sts16(gi, cs); sts16(gi + 128, -sn); sts16(gi + 256, sn); sts16(gi + 384, cs);
            }
            sincospif((float)(8 * w + g) * (1.f / 128.f), &sn, &cs);
            w1 = make_float2(cs, -sn); w2 = cmul(w1, w1); w3 = cmul(w1, w2);
        }
        const uint32_t ua = sb + OFF_U + (lane >> 4) * 16384 + (8 * w + (lane & 7)) * 128 + ((((lane >> 3) & 1) ^ (lane & 7)) << 4);
        if (main_cta) {
            mbar_wait(bars + 8 * BAR_X, 0);
            if (t == 0) {
                PROF(8);
            }
            __syncwarp();
#pragma unroll 1
            for (int hf = 0; hf < 2; hf++) {
                float acc[64];
                const uint64_t da = make_desc(sb + OFF_F, 16, 1024), db = make_desc(sb + OFF_W + hf * 16384, 4096, 512, 2);
                wgmma_fence();
                wgmma_n128<0>(acc, da, db); wgmma_n128<1>(acc, da + 2, db + 64); wgmma_n128<1>(acc, da + 4, db + 128); wgmma_n128<1>(acc, da + 6, db + 192);
                wgmma_commit();
                wgmma_wait<0>();
#pragma unroll
                for (int jp = 0; jp < 2; jp++) {
                    float2 y[4][4];
#pragma unroll
                    for (int i = 0; i < 4; i++) {
                        const int o = 8 * jp + 4 * (i >> 1) + (i & 1);
#pragma unroll
                        for (int m = 0; m < 4; m++) y[i][m] = make_float2(acc[16 * m + o], acc[16 * m + o + 2]);
                    }
                    if (special) {
#pragma unroll
                        for (int i = 0; i < 4; i++) {
                            const float2 s0 = cadd(y[i][0], y[i][2]), s1 = csub(y[i][0], y[i][2]), s2 = cadd(y[i][1], y[i][3]), s3 = csub(y[i][1], y[i][3]);
                            const float b0 = y[i][0].y, b2 = y[i][2].y;
                            y[i][0] = make_float2(s0.x + s2.x, s0.x - s2.x);
                            y[i][1] = make_float2(s1.x, -s3.x);
                            y[i][2] = make_float2(fmaf(R, s3.y, b0), fmaf(-R, s2.y, -b2));
                            y[i][3] = make_float2(fmaf(-R, s3.y, b0), fmaf(-R, s2.y, b2));
                        }
                    } else {
#pragma unroll
                        for (int i = 0; i < 4; i++) {
                            y[i][1] = cmul(y[i][1], w1); y[i][2] = cmul(y[i][2], w2); y[i][3] = cmul(y[i][3], w3);
                            fft4(y[i][0], y[i][1], y[i][2], y[i][3]);
                        }
                    }
                    __syncwarp();
#pragma unroll
                    for (int c = 0; c < 4; c++)
                        stsm_x4((ua ^ (hf * 64 + jp * 32)) + c * 4096, pack2(y[0][c].x, y[1][c].x), pack2(y[2][c].x, y[3][c].x),
                                pack2(y[0][c].y, y[1][c].y), pack2(y[2][c].y, y[3][c].y));
                }
            }
        }
        fence_proxy_async_smem();
        helper_sync();
        if (t == 0) {
            PROF(21);
            if (main_cta) {
                tma_store_4d(&mapU1, sb + OFF_U, (b & 15) * 64, 0, 0, b >> 4);
                tma_store_4d(&mapU1, sb + OFF_U + 16384, (b & 15) * 64, 0, 1, b >> 4);
                bulk_commit();
            }
            if (main_cta) {
                PROF(22);
                bulk_wait0();
                signal_counter(&g_cnt[CNT_U * 32]);
                PROF(9);
            }
            mbar_expect_tx(bars + 8 * BAR_W, 2 * 9216);
            mbar_expect_tx(bars + 8 * BAR_W2, 2 * 9216);
#pragma unroll 1
            for (int i = 0; i < 4; i++) {
                pace(prog);
                tma_load_3d(sb + OFF_W + (i >> 1) * 9216 + (i & 1) * 18432, &mapWr + (i & 1), bars + 8 * (i < 2 ? BAR_W : BAR_W2), 0,
                            (1026 * (i < 2 ? cls : (256 - cls) & 255)) >> 7, 0);
            }
            PROF(10);
        }
        __syncwarp();
        mbar_wait(bars + 8 * BAR_W, 0);
        mbar_wait(bars + 8 * BAR_W2, 0);
#pragma unroll 1
        for (int rr = 0; rr < 4; rr++) {
            if (t == 0) {
                const uint32_t bu = bars + 8 * BAR_U;
                if (rr == 0) {
                    mbar_expect_tx(bu, 32768 + 12288);
                    bulk_load(sb + OFF_F, c_tab + 2048, 12288, bu);
                } else if (rr < 3) {
                    wait_counter(&g_cnt[CNT_U * 32], epoch * 128);
                    PROF(11);
                    tma_load_4d(sb + OFF_U + (rr - 1) * 16384, &mapU2, bu, 0, 0, 0, b == 128 ? 1 : b == 0 ? 0 : 2 * b + rr - 1);
                }
            }
            __syncwarp();
            const int row = 2 * w + (rr >> 1), mrow = b == 0 ? (8 - row) & 7 : 7 - row, mir = rr & 1;
            const uint32_t dp = OFF_W + row * 1152, mp = OFF_W + 9216 + mrow * 1152;
            const uint32_t dbase = dp + ((1026 * cls) & 127), mbase = mp + ((1026 * (256 - cls)) & 127);
            const int sg = mir ? -1 : 1;
            const uint32_t a0 = (mir ? mbase + 1024 : dbase) + sg * (2 * g + 128 * q);
            uint32_t wv[2][2][4];
#pragma unroll
            for (int h = 0; h < 2; h++)
#pragma unroll
                for (int j = 0; j < 2; j++)
#pragma unroll
                    for (int i = 0; i < 4; i++) {
                        const uint32_t ad = sb + swz(a0 + sg * (32 * h + 16 * (i >> 1) + 512 * j + 64 * (i & 1)));
                        wv[h][j][i] = (lds16(ad) | (lds16(ad + 18432) << 16)) ^ (mir << 31);
                    }
            if (lane == 0) {
                const uint32_t a2 = sb + swz(mir ? dbase + 1024 : mbase);
                wv[0][0][0] = pack2(0.5f * (bf_lo(wv[0][0][0]) + bf_lo(lds16(a2))), 0.5f * (bf_hi(wv[0][0][0]) - sg * bf_lo(lds16(a2 + 18432))));
            }
            __syncwarp();
#pragma unroll
            for (int h = 0; h < 2; h++)
#pragma unroll
                for (int j = 0; j < 2; j++)
                    sts128u(sb + (mir ? mp : dp) + h * 18432 + j * 512 + lane * 16, wv[h][j][0], wv[h][j][1], wv[h][j][2], wv[h][j][3]);
        }
        fence_proxy_async_smem();
        if (t == 0) PROF(12);
#pragma unroll 1
        for (int dir = 0; dir < 2; dir++) {
            if (dir == 0) {
                mbar_wait(bars + 8 * BAR_U, 0);
                if (main_cta) mbar_wait(bars + 8 * BAR_G1, 0);
            } else {
                if (t == 0 && main_cta) {
                    mbar_wait(bars + 8 * BAR_H, 0);
                    bulk_store(g_gate + 16 * b, sb + OFF_GS, 128);
                    tma_store_3d(&mapH2, sb + STAGE_BYTES + 16384, (b >> 4) * 32, P.swapB * 1024 + (b & 15) * 64, 0);
                    tma_store_3d(&mapH2, sb + 2 * STAGE_BYTES + 16384, (b >> 4) * 32, (P.swapB ^ 1) * 1024 + (b & 15) * 64, 0);
                    bulk_commit();
                    bulk_wait0();
                    PROF(26);
                        signal_counter(&g_cnt[CNT_H * 32]);
                    wait_counter(&g_cnt[CNT_H * 32], epoch * 128);
                        PROF(1);
#pragma unroll 1
                    for (int k = 0; k < NSTAGE; k++) {
                        const int s = k == 2 ? 0 : k + 1;
                        tma_load_3d(sb + s * STAGE_BYTES + 16384, &mapH, bars + 8 * (BAR_FULL + s), 0, (b & 1) * 1024 + k * 64, (b >> 4) * 4);
                    }
                }
                __syncwarp();
                mbar_wait(bars + 8 * BAR_CD, 0);
            }
            helper_radix8(sb, sb + OFF_G + dir * 512, w, lane);
            if (dir == 0) mbar_arrive(bars + 8 * BAR_C);
        }
        fence_proxy_async_smem();
        helper_sync();
        if (t == 0) {
            PROF(24);
            tma_store_4d(&mapU2, sb + OFF_U, 0, 0, 0, b == 128 ? 1 : 2 * b);
            if (!real_cls) tma_store_4d(&mapU2, sb + OFF_U + 16384, 0, 0, 0, 2 * b + 1);
            bulk_commit();
            bulk_wait0();
            signal_counter(&g_cnt[CNT_V * 32]);
            PROF(13);
            if (main_cta) {
                wait_counter(&g_cnt[CNT_V * 32], epoch * 129);
                mbar_expect_tx(bars + 8 * BAR_U, 32768);
                PROF(14);
                tma_load_4d(sb + OFF_U, &mapU1, bars + 8 * BAR_U, (b & 15) * 64, 0, 0, b >> 4);
                pace(prog);
                tma_load_4d(sb + OFF_U + 16384, &mapU1, bars + 8 * BAR_U, (b & 15) * 64, 0, 1, b >> 4);
            }
        } else if (t == 32 && main_cta) {
            load_x_tile(true);
        }
        if (main_cta) {
            helper_sync();
#pragma unroll
            for (int i = 0; i < 2; i++) {
                const int m0 = 2 * i + (t >> 6), m1 = t & 63;
                const int tt = (b >> 4) + 8 * m0 + 32 * m1;
                const float2 gv = __ldcg(&g_gate[(tt & ~255) + ((tt & 62) << 2) + ((tt >> 5) & 6) + (tt & 1)]);
                *(float2*)(sm + OFF_GT + m0 * 512 + m1 * 8) = gv;
                *(float*)(sm + OFF_S + m0 * 272 + m1 * 4) = ((b & 1) ? -2.f : 2.f) * gv.y;
            }
            uint32_t dk[2];
#pragma unroll
            for (int hh = 0; hh < 2; hh++) dk[hh] = (uint32_t)__ldg((const unsigned short*)P.dskip + (b & 15) * 64 + 16 * w + 8 * hh + g) * 0x10001u;
            mbar_wait(bars + 8 * BAR_U, 1);
            if (t == 0) PROF(25);
            w1.y = -w1.y; w2.y = -w2.y; w3.y = -w3.y;
#pragma unroll 1
            for (int cp = 0; cp < 4; cp++) {
                float2 y[4][4];
#pragma unroll
                for (int c = 0; c < 4; c++) {
                    uint32_t r[4];
                    ldsm_x4(r, (ua ^ (cp * 32)) + c * 4096);
                    y[0][c] = make_float2(bf_lo(r[0]), bf_lo(r[2])); y[1][c] = make_float2(bf_hi(r[0]), bf_hi(r[2]));
                    y[2][c] = make_float2(bf_lo(r[1]), bf_lo(r[3])); y[3][c] = make_float2(bf_hi(r[1]), bf_hi(r[3]));
                }
                if (special) {
#pragma unroll
                    for (int i = 0; i < 4; i++) {
                        const float ap = 0.5f * (y[i][0].x + y[i][0].y), am = 0.5f * (y[i][0].x - y[i][0].y);
                        const float2 u = y[i][1], sp = cadd(y[i][2], y[i][3]), sd = csub(y[i][2], y[i][3]);
                        y[i][0] = make_float2(ap + u.x, sp.x);
                        y[i][1] = make_float2(am - u.y, R * (sd.x - sp.y));
                        y[i][2] = make_float2(ap - u.x, -sd.y);
                        y[i][3] = make_float2(am + u.y, -R * (sd.x + sp.y));
                    }
                } else {
#pragma unroll
                    for (int i = 0; i < 4; i++) {
                        fft4(y[i][0], y[i][3], y[i][2], y[i][1]);
                        const float2 o1 = y[i][3];
                        y[i][3] = cmul(y[i][1], w3); y[i][1] = cmul(o1, w1); y[i][2] = cmul(y[i][2], w2);
                    }
                }
                __syncwarp();
#pragma unroll
                for (int c = 0; c < 4; c++)
                    stsm_x4((ua ^ (cp * 32)) + c * 4096, pack2(y[0][c].x, y[1][c].x), pack2(y[2][c].x, y[3][c].x),
                            pack2(y[0][c].y, y[1][c].y), pack2(y[2][c].y, y[3][c].y));
            }
            fence_proxy_async_smem();
            mbar_wait(bars + 8 * BAR_X, 1);
            helper_sync();
            if (t == 0) PROF(15);
            const uint64_t dfb = make_desc(sb + OFF_F, 16, 1024);
            const uint32_t xrow = (lane & 7) + 8 * (lane >> 4);
            const uint32_t xa = sb + OFF_W + (w >> 1) * 16384 + xrow * 64 + (((2 * (w & 1) + ((lane >> 3) & 1)) ^ ((xrow >> 1) & 3)) << 4);
            const uint32_t eo = (w >> 1) * 16384 + (w & 1) * 2048 + g * 64 + q * 16;
#pragma unroll 1
            for (int mp = 0; mp < 2; mp++) {
                float acc[2][32];
                wgmma_fence();
#pragma unroll
                for (int c = 0; c < 2; c++) {
                    const uint64_t da = make_desc(sb + OFF_U + (2 * mp + c) * 4096, 16, 16384);
                    wgmma_n64<0>(acc[c], da, dfb); wgmma_n64<1>(acc[c], da + 64, dfb + 128);
                    wgmma_n64<1>(acc[c], da + 128, dfb + 256); wgmma_n64<1>(acc[c], da + 192, dfb + 384);
                    wgmma_commit();
                }
#pragma unroll
                for (int c = 0; c < 2; c++) {
                    const int m0 = 2 * mp + c;
                    uint32_t xv[4][4];
#pragma unroll
                    for (int jj = 0; jj < 4; jj++) ldsm_x4_t(xv[jj], xa + m0 * 4096 + jj * 1024);
                    if (c == 0) wgmma_wait<1>(); else wgmma_wait<0>();
                    helper_sync();
#pragma unroll
                    for (int jj = 0; jj < 4; jj++) {
                        const float4 g0 = lds128(sb + OFF_GT + m0 * 512 + jj * 128 + q * 16), g1 = lds128(sb + OFF_GT + m0 * 512 + jj * 128 + 64 + q * 16);
#pragma unroll
                        for (int hh = 0; hh < 2; hh++) {
                            const uint32_t p0 = bf_mul2(xv[jj][hh], dk[hh]), p1 = bf_mul2(xv[jj][2 + hh], dk[hh]);
                            const float* a = &acc[c][8 * jj + 2 * hh];
                            sts128(sb + (hh ? OFF_W : OFF_U) + m0 * 4096 + jj * 512 + (eo ^ (m0 << 4)),
                                   fmaf(g0.x, a[0], g0.y * bf_lo(p0)), fmaf(g0.z, a[1], g0.w * bf_hi(p0)),
                                   fmaf(g1.x, a[4], g1.y * bf_lo(p1)), fmaf(g1.z, a[5], g1.w * bf_hi(p1)));
                        }
                    }
                }
            }
            mbar_arrive(bars + 8 * BAR_E);
            if (t == 0) PROF(20);
            cluster_wait();
        }
    }
}

typedef CUresult (*PFN_encodeTiled)(CUtensorMap*, CUtensorMapDataType, cuuint32_t, void*, const cuuint64_t*, const cuuint64_t*,
                                    const cuuint32_t*, const cuuint32_t*, CUtensorMapInterleave, CUtensorMapSwizzle,
                                    CUtensorMapL2promotion, CUtensorMapFloatOOBfill);

static CUtensorMap make_map(PFN_encodeTiled enc, const void* ptr, int rank, const cuuint64_t* dims, const cuuint64_t* strides, const cuuint32_t* box,
                            CUtensorMapSwizzle sw = CU_TENSOR_MAP_SWIZZLE_128B) {
    CUtensorMap m;
    cuuint32_t es[5] = {1, 1, 1, 1, 1};
    enc(&m, CU_TENSOR_MAP_DATA_TYPE_BFLOAT16, rank, (void*)ptr, dims, strides, box, es, CU_TENSOR_MAP_INTERLEAVE_NONE,
        sw, CU_TENSOR_MAP_L2_PROMOTION_L2_128B, CU_TENSOR_MAP_FLOAT_OOB_FILL_NONE);
    return m;
}

extern "C" void kernel_launch(void* const* d_in, const int* in_sizes, int n_in, void* d_out, int out_size) {
    const bf16* x = (const bf16*)d_in[0];
    const bf16* wr = (const bf16*)d_in[1];
    const bf16* wi = (const bf16*)d_in[2];
    const bf16* Bre = (const bf16*)d_in[6];
    const bf16* Bim = (const bf16*)d_in[7];
    const bf16* Cre = (const bf16*)d_in[8];
    const bf16* Cim = (const bf16*)d_in[9];

    void* fn = nullptr;
    cudaDriverEntryPointQueryResult st;
    cudaGetDriverEntryPoint("cuTensorMapEncodeTiled", &fn, cudaEnableDefault, &st);
    PFN_encodeTiled enc = (PFN_encodeTiled)fn;
    void *p_hT, *p_U;
    cudaGetSymbolAddress(&p_hT, g_hT);
    cudaGetSymbolAddress(&p_U, g_U);

    Params P;
    P.x = x; P.lam_re = (const bf16*)d_in[4]; P.lam_im = (const bf16*)d_in[5]; P.log_dt = (const bf16*)d_in[10];
    P.dskip = (const bf16*)d_in[11]; P.gate_w = (const bf16*)d_in[12]; P.c_re = Cre; P.c_im = Cim; P.b_re = Bre; P.b_im = Bim; P.w_r = wr; P.w_i = wi; P.out = (float*)d_out;
    P.swapB = Bim < Bre;

    CUtensorMap mB, mX, mH, mCre, mCim, mXs, mU1, mU2, mWr, mWi, mH2;
    {
        const bf16* lo = P.swapB ? Bim : Bre; const bf16* hi = P.swapB ? Bre : Bim;
        cuuint64_t d[4] = {1024, 8, 2, 128}, s[3] = {2048, (cuuint64_t)((const char*)hi - (const char*)lo), 16384};
        cuuint32_t bx[4] = {64, 8, 2, 8};
        mB = make_map(enc, lo, 4, d, s, bx);
    }
    {
        cuuint64_t d[4] = {1024, 2, 4, 928}, s[3] = {2048, 64 * 2048, 2 * 2048};
        cuuint32_t bx[4] = {64, 2, 4, 32};
        mX = make_map(enc, x, 4, d, s, bx);
    }
    {
        cuuint64_t d[3] = {64, 2048, 32}, s[2] = {4096, 128};
        cuuint32_t bx[3] = {64, 64, 4};
        mH = make_map(enc, p_hT, 3, d, s, bx);
    }
    {
        cuuint64_t d[4] = {1024, 8, 2, 120}, s[3] = {2048, 64 * 2048, 8 * 2048};
        cuuint32_t bx[4] = {64, 8, 2, 8};
        mCre = make_map(enc, Cre, 4, d, s, bx);
        mCim = make_map(enc, Cim, 4, d, s, bx);
    }
    {
        cuuint64_t d[4] = {1024, 64, 4, 8}, s[3] = {32 * 2048, 8 * 2048, 2048};
        cuuint32_t bx[4] = {32, 64, 4, 1};
        mXs = make_map(enc, x, 4, d, s, bx, CU_TENSOR_MAP_SWIZZLE_64B);
    }
    {
        cuuint64_t d[4] = {1024, 128, 2, 8}, s[3] = {32768, 16384, 2048};
        cuuint32_t bx[4] = {64, 128, 1, 1};
        mU1 = make_map(enc, p_U, 4, d, s, bx);
    }
    {
        cuuint64_t d[4] = {64, 8, 16, 256}, s[3] = {2048, 128, 16384};
        cuuint32_t bx[4] = {64, 8, 16, 1};
        mU2 = make_map(enc, p_U, 4, d, s, bx);
    }
    {
        cuuint64_t d[3] = {64, 2052, 8}, s[2] = {128, 262656};
        cuuint32_t bx[3] = {64, 9, 8};
        mWr = make_map(enc, wr, 3, d, s, bx);
        mWi = make_map(enc, wi, 3, d, s, bx);
    }
    {
        cuuint64_t d[3] = {256, 2048, 8}, s[2] = {4096, 512};
        cuuint32_t bx[3] = {32, 64, 8};
        mH2 = make_map(enc, p_hT, 3, d, s, bx, CU_TENSOR_MAP_SWIZZLE_NONE);
    }
    cudaFuncSetAttribute(fused_kernel, cudaFuncAttributeMaxDynamicSharedMemorySize, SMEM_BYTES);
    fused_kernel<<<130, 384, SMEM_BYTES, cudaStreamPerThread>>>(mB, mX, mH, mCre, mCim, mXs, mU1, mU2, mWr, mWi, mH2, P);
}
```

```cpp
#include <cuda_runtime.h>
#include <cuda_bf16.h>
#include <cuda_fp16.h>
#include <cuda.h>
#include <stdint.h>

typedef __nv_bfloat16 bf16;

__device__ const __align__(128) uint32_t c_tab[5120] = {
0x3f803f80,0xbf803f80,0x3f803f80,0xbf803f80,0x3f803f80,0xbf803f80,0x3f803f80,0xbf803f80,0x3f803f80,0xbf803f80,0x3f803f80,0xbf803f80,
0x3f803f80,0xbf803f80,0x3f803f80,0xbf803f80,0x3f7f3f80,0xbdc98000,0x3f223f35,0xbf46bf35,0x3f753f7b,0xbe95be48,0x3ef13f0e,0xbf62bf55,
0x3f623f6d,0xbef1bec4,0x3e953ec4,0xbf75bf6d,0x3f463f55,0xbf22bf0e,0x3dc93e48,0xbf7fbf7b,0x3f7b3f80,0xbe488000,0xbe480000,0xbf7bbf80,
0x3f553f6d,0xbf0ebec4,0xbf0ebec4,0xbf55bf6d,0x3f0e3f35,0xbf55bf35,0xbf55bf35,0xbf0ebf35,0x3e483ec4,0xbf7bbf6d,0xbf7bbf6d,0xbe48bec4,
0x3f753f80,0xbe958000,0xbf62bf35,0xbef1bf35,0x3f223f55,0xbf46bf0e,0xbf7fbf7b,0x3dc9be48,0x3dc93ec4,0xbf7fbf6d,0xbf46bf6d,0x3f223ec4,
0xbef1be48,0xbf62bf7b,0xbe95bf0e,0x3f753f55,0x3f6d3f80,0xbec48000,0xbf6dbf80,0x3ec48000,0x3ec43f35,0xbf6dbf35,0xbec4bf35,0x3f6d3f35,
0xbec40000,0xbf6dbf80,0x3ec40000,0x3f6d3f80,0xbf6dbf35,0xbec4bf35,0x3f6d3f35,0x3ec43f35,0x3f623f80,0xbef18000,0xbe95bf35,0x3f753f35,
0x3dc93f0e,0xbf7fbf55,0x3f223e48,0x3f463f7b,0xbf46bec4,0xbf22bf6d,0x3f7f3f6d,0xbdc93ec4,0xbf75bf7b,0x3e95be48,0x3ef13f55,0xbf62bf0e,
0x3f553f80,0xbf0e8000,0x3f0e0000,0x3f553f80,0xbe483ec4,0xbf7bbf6d,0x3f7b3f6d,0xbe483ec4,0xbf7bbf35,0xbe48bf35,0x3e483f35,0xbf7bbf35,
0xbf0ebf6d,0x3f553ec4,0xbf55bec4,0xbf0ebf6d,0x3f463f80,0xbf228000,0x3f7f3f35,0x3dc93f35,0xbef13e48,0xbf62bf7b,0x3e953f55,0xbf75bf0e,
0xbf75bf6d,0x3e95bec4,0xbf62bec4,0xbef1bf6d,0x3dc9bf0e,0x3f7f3f55,0xbf22bf7b,0x3f463e48,0x3f353f80,0xbf358000,0x3f353f80,0xbf358000,
0xbf350000,0xbf35bf80,0xbf350000,0xbf35bf80,0xbf35bf80,0x3f358000,0xbf35bf80,0x3f358000,0x3f350000,0x3f353f80,0x3f350000,0x3f353f80,
0x3f223f80,0xbf468000,0xbdc93f35,0xbf7fbf35,0xbf62be48,0xbef1bf7b,0xbf75bf55,0x3e95bf0e,0xbe95bf6d,0x3f753ec4,0x3ef1bec4,0x3f623f6d,
0x3f7f3f0e,0x3dc93f55,0x3f463f7b,0xbf223e48,0x3f0e3f80,0xbf558000,0xbf550000,0xbf0ebf80,0xbf7bbec4,0xbe48bf6d,0xbe48bf6d,0x3f7b3ec4,
0x3e48bf35,0x3f7b3f35,0x3f7b3f35,0xbe483f35,0x3f553f6d,0xbf0e3ec4,0xbf0e3ec4,0xbf55bf6d,0x3ef13f80,0xbf628000,0xbf75bf35,0x3e95bf35,
0xbf7fbf0e,0x3dc9bf55,0x3f46be48,0x3f223f7b,0x3f22bec4,0x3f463f6d,0x3dc93f6d,0xbf7fbec4,0x3e953f7b,0xbf75be48,0xbf62bf55,0x3ef1bf0e,
0x3ec43f80,0xbf6d8000,0xbec4bf80,0x3f6d8000,0xbf6dbf35,0x3ec4bf35,0x3f6d3f35,0xbec43f35,0x3f6d0000,0x3ec43f80,0xbf6d0000,0xbec4bf80,
0xbec43f35,0xbf6dbf35,0x3ec4bf35,0x3f6d3f35,0x3e953f80,0xbf758000,0x3ef1bf35,0x3f623f35,0xbf46bf55,0x3f22bf0e,0x3dc93f7b,0xbf7fbe48,
0x3f7f3ec4,0xbdc93f6d,0xbf22bf6d,0x3f46bec4,0xbf623e48,0xbef1bf7b,0x3f753f0e,0xbe953f55,0x3e483f80,0xbf7b8000,0x3f7b0000,0x3e483f80,
0xbf0ebf6d,0x3f55bec4,0xbf553ec4,0xbf0ebf6d,0x3f553f35,0xbf0e3f35,0x3f0ebf35,0x3f553f35,0xbf7bbec4,0x3e48bf6d,0xbe483f6d,0xbf7bbec4,
0x3dc93f80,0xbf7f8000,0x3f463f35,0xbf223f35,0xbe95bf7b,0x3f75be48,0xbf62bf0e,0x3ef1bf55,0x3ef13f6d,0xbf623ec4,0x3f753ec4,0xbe953f6d,
0xbf22bf55,0x3f46bf0e,0xbf7fbe48,0x3dc9bf7b,0x3f80,0xbf808000,0x3f80,0xbf808000,0xbf80,0x3f808000,0xbf80,0x3f808000,
0x3f80,0xbf808000,0x3f80,0xbf808000,0xbf80,0x3f808000,0xbf80,0x3f808000,0xbdc93f80,0xbf7f8000,0xbf463f35,0xbf22bf35,
0x3e95bf7b,0x3f753e48,0x3f62bf0e,0x3ef13f55,0xbef13f6d,0xbf62bec4,0xbf753ec4,0xbe95bf6d,0x3f22bf55,0x3f463f0e,0x3f7fbe48,0x3dc93f7b,
0xbe483f80,0xbf7b8000,0xbf7b0000,0x3e48bf80,0x3f0ebf6d,0x3f553ec4,0x3f553ec4,0xbf0e3f6d,0xbf553f35,0xbf0ebf35,0xbf0ebf35,0x3f55bf35,
0x3f7bbec4,0x3e483f6d,0x3e483f6d,0xbf7b3ec4,0xbe953f80,0xbf758000,0xbef1bf35,0x3f62bf35,0x3f46bf55,0x3f223f0e,0xbdc93f7b,0xbf7f3e48,
0xbf7f3ec4,0xbdc9bf6d,0x3f22bf6d,0x3f463ec4,0x3f623e48,0xbef13f7b,0xbf753f0e,0xbe95bf55,0xbec43f80,0xbf6d8000,0x3ec4bf80,0x3f6d8000,
0x3f6dbf35,0x3ec43f35,0xbf6d3f35,0xbec4bf35,0xbf6d0000,0x3ec4bf80,0x3f6d0000,0xbec43f80,0x3ec43f35,0xbf6d3f35,0xbec4bf35,0x3f6dbf35,
0xbef13f80,0xbf628000,0x3f75bf35,0x3e953f35,0x3f7fbf0e,0x3dc93f55,0xbf46be48,0x3f22bf7b,0xbf22bec4,0x3f46bf6d,0xbdc93f6d,0xbf7f3ec4,
0xbe953f7b,0xbf753e48,0x3f62bf55,0x3ef13f0e,0xbf0e3f80,0xbf558000,0x3f550000,0xbf0e3f80,0x3f7bbec4,0xbe483f6d,0x3e48bf6d,0x3f7bbec4,
0xbe48bf35,0x3f7bbf35,0xbf7b3f35,0xbe48bf35,0xbf553f6d,0xbf0ebec4,0x3f0e3ec4,0xbf553f6d,0xbf223f80,0xbf468000,0x3dc93f35,0xbf7f3f35,
0x3f62be48,0xbef13f7b,0x3f75bf55,0x3e953f0e,0x3e95bf6d,0x3f75bec4,0xbef1bec4,0x3f62bf6d,0xbf7f3f0e,0x3dc9bf55,0xbf463f7b,0xbf22be48,
0xbf353f80,0xbf358000,0xbf353f80,0xbf358000,0x3f350000,0xbf353f80,0x3f350000,0xbf353f80,0x3f35bf80,0x3f358000,0x3f35bf80,0x3f358000,
0xbf350000,0x3f35bf80,0xbf350000,0x3f35bf80,0xbf463f80,0xbf228000,0xbf7f3f35,0x3dc9bf35,0x3ef13e48,0xbf623f7b,0xbe953f55,0xbf753f0e,
0x3f75bf6d,0x3e953ec4,0x3f62bec4,0xbef13f6d,0xbdc9bf0e,0x3f7fbf55,0x3f22bf7b,0x3f46be48,0xbf553f80,0xbf0e8000,0xbf0e0000,0x3f55bf80,
0x3e483ec4,0xbf7b3f6d,0xbf7b3f6d,0xbe48bec4,0x3f7bbf35,0xbe483f35,0xbe483f35,0xbf7b3f35,0x3f0ebf6d,0x3f55bec4,0x3f55bec4,0xbf0e3f6d,
0xbf623f80,0xbef18000,0x3e95bf35,0x3f75bf35,0xbdc93f0e,0xbf7f3f55,0xbf223e48,0x3f46bf7b,0x3f46bec4,0xbf223f6d,0xbf7f3f6d,0xbdc9bec4,
0x3f75bf7b,0x3e953e48,0xbef13f55,0xbf623f0e,0xbf6d3f80,0xbec48000,0x3f6dbf80,0x3ec48000,0xbec43f35,0xbf6d3f35,0x3ec4bf35,0x3f6dbf35,
0x3ec40000,0xbf6d3f80,0xbec40000,0x3f6dbf80,0x3f6dbf35,0xbec43f35,0xbf6d3f35,0x3ec4bf35,0xbf753f80,0xbe958000,0x3f62bf35,0xbef13f35,
0xbf223f55,0xbf463f0e,0x3f7fbf7b,0x3dc93e48,0xbdc93ec4,0xbf7f3f6d,0x3f46bf6d,0x3f22bec4,0x3ef1be48,0xbf623f7b,0x3e95bf0e,0x3f75bf55,
0xbf7b3f80,0xbe488000,0x3e480000,0xbf7b3f80,0xbf553f6d,0xbf0e3ec4,0x3f0ebec4,0xbf553f6d,0xbf0e3f35,0xbf553f35,0x3f55bf35,0xbf0e3f35,
0xbe483ec4,0xbf7b3f6d,0x3f7bbf6d,0xbe483ec4,0xbf7f3f80,0xbdc98000,0xbf223f35,0xbf463f35,0xbf753f7b,0xbe953e48,0xbef13f0e,0xbf623f55,
0xbf623f6d,0xbef13ec4,0xbe953ec4,0xbf753f6d,0xbf463f55,0xbf223f0e,0xbdc93e48,0xbf7f3f7b,0x3f803f80,0xbf803f80,0x3f803f80,0xbf803f80,
0x3f803f80,0xbf803f80,0x3f803f80,0xbf803f80,0x3f803f80,0xbf803f80,0x3f803f80,0xbf803f80,0x3f803f80,0xbf803f80,0x3f803f80,0xbf803f80,
0xbdc90000,0xbf7fbf80,0xbf46bf35,0xbf22bf35,0xbe95be48,0xbf75bf7b,0xbf62bf55,0xbef1bf0e,0xbef1bec4,0xbf62bf6d,0xbf75bf6d,0xbe95bec4,
0xbf22bf0e,0xbf46bf55,0xbf7fbf7b,0xbdc9be48,0xbf7bbf80,0x3e488000,0x3e480000,0x3f7b3f80,0xbf55bf6d,0x3f0e3ec4,0x3f0e3ec4,0x3f553f6d,
0xbf0ebf35,0x3f553f35,0x3f553f35,0x3f0e3f35,0xbe48bec4,0x3f7b3f6d,0x3f7b3f6d,0x3e483ec4,0x3e950000,0x3f753f80,0x3ef13f35,0xbf62bf35,
0x3f463f0e,0x3f223f55,0xbdc93e48,0xbf7fbf7b,0x3f7f3f6d,0x3dc93ec4,0xbf22bec4,0xbf46bf6d,0x3f623f7b,0xbef1be48,0xbf75bf55,0xbe95bf0e,
0x3f6d3f80,0xbec48000,0xbf6dbf80,0x3ec48000,0x3ec43f35,0xbf6dbf35,0xbec4bf35,0x3f6d3f35,0xbec40000,0xbf6dbf80,0x3ec40000,0x3f6d3f80,
0xbf6dbf35,0xbec4bf35,0x3f6d3f35,0x3ec43f35,0xbef10000,0xbf62bf80,0x3f753f35,0x3e953f35,0xbf7fbf55,0xbdc9bf0e,0x3f463f7b,0xbf22be48,
0xbf22bf6d,0x3f463ec4,0xbdc93ec4,0xbf7fbf6d,0x3e95be48,0x3f753f7b,0xbf62bf0e,0xbef1bf55,0xbf55bf80,0x3f0e8000,0xbf0e0000,0xbf55bf80,
0x3e48bec4,0x3f7b3f6d,0xbf7bbf6d,0x3e48bec4,0x3f7b3f35,0x3e483f35,0xbe48bf35,0x3f7b3f35,0x3f0e3f6d,0xbf55bec4,0x3f553ec4,0x3f0e3f6d,
0x3f220000,0x3f463f80,0xbdc9bf35,0x3f7f3f35,0x3f623f7b,0xbef13e48,0x3f753f0e,0x3e953f55,0xbe953ec4,0xbf75bf6d,0x3ef13f6d,0xbf62bec4,
0xbf7fbf55,0x3dc9bf0e,0xbf46be48,0xbf22bf7b,0x3f353f80,0xbf358000,0x3f353f80,0xbf358000,0xbf350000,0xbf35bf80,0xbf350000,0xbf35bf80,
0xbf35bf80,0x3f358000,0xbf35bf80,0x3f358000,0x3f350000,0x3f353f80,0x3f350000,0x3f353f80,0xbf460000,0xbf22bf80,0xbf7fbf35,0x3dc9bf35,
0xbef1bf7b,0x3f623e48,0x3e95bf0e,0x3f753f55,0x3f753ec4,0x3e953f6d,0x3f623f6d,0xbef13ec4,0x3dc93f55,0xbf7fbf0e,0xbf223e48,0xbf46bf7b,
0xbf0ebf80,0x3f558000,0x3f550000,0x3f0e3f80,0x3f7b3ec4,0x3e483f6d,0x3e483f6d,0xbf7bbec4,0xbe483f35,0xbf7bbf35,0xbf7bbf35,0x3e48bf35,
0xbf55bf6d,0x3f0ebec4,0x3f0ebec4,0x3f553f6d,0x3f620000,0x3ef13f80,0xbe953f35,0xbf75bf35,0xbdc93f55,0xbf7fbf0e,0xbf22bf7b,0x3f46be48,
0xbf46bf6d,0x3f22bec4,0x3f7f3ec4,0x3dc93f6d,0x3f753e48,0x3e953f7b,0xbef13f0e,0xbf62bf55,0x3ec43f80,0xbf6d8000,0xbec4bf80,0x3f6d8000,
0xbf6dbf35,0x3ec4bf35,0x3f6d3f35,0xbec43f35,0x3f6d0000,0x3ec43f80,0xbf6d0000,0xbec4bf80,0xbec43f35,0xbf6dbf35,0x3ec4bf35,0x3f6d3f35,
0xbf750000,0xbe95bf80,0x3f623f35,0xbef13f35,0x3f22bf0e,0x3f463f55,0xbf7fbe48,0xbdc9bf7b,0xbdc93f6d,0xbf7fbec4,0x3f46bec4,0x3f223f6d,
0xbef1bf7b,0x3f62be48,0xbe953f55,0xbf75bf0e,0xbe48bf80,0x3f7b8000,0xbf7b0000,0xbe48bf80,0x3f0e3f6d,0xbf553ec4,0x3f55bec4,0x3f0e3f6d,
0xbf55bf35,0x3f0ebf35,0xbf0e3f35,0xbf55bf35,0x3f7b3ec4,0xbe483f6d,0x3e48bf6d,0x3f7b3ec4,0x3f7f0000,0x3dc93f80,0x3f22bf35,0x3f463f35,
0xbf753e48,0xbe95bf7b,0xbef13f55,0xbf62bf0e,0x3f62bec4,0x3ef13f6d,0x3e95bf6d,0x3f753ec4,0xbf463f0e,0xbf22bf55,0xbdc93f7b,0xbf7fbe48,
0x3f80,0xbf808000,0x3f80,0xbf808000,0xbf80,0x3f808000,0xbf80,0x3f808000,0x3f80,0xbf808000,0x3f80,0xbf808000,
0xbf80,0x3f808000,0xbf80,0x3f808000,0xbf7f0000,0x3dc9bf80,0xbf22bf35,0x3f46bf35,0x3f753e48,0xbe953f7b,0x3ef13f55,0xbf623f0e,
0xbf62bec4,0x3ef1bf6d,0xbe95bf6d,0x3f75bec4,0x3f463f0e,0xbf223f55,0x3dc93f7b,0xbf7f3e48,0x3e48bf80,0x3f7b8000,0x3f7b0000,0xbe483f80,
0xbf0e3f6d,0xbf55bec4,0xbf55bec4,0x3f0ebf6d,0x3f55bf35,0x3f0e3f35,0x3f0e3f35,0xbf553f35,0xbf7b3ec4,0xbe48bf6d,0xbe48bf6d,0x3f7bbec4,
0x3f750000,0xbe953f80,0xbf623f35,0xbef1bf35,0xbf22bf0e,0x3f46bf55,0x3f7fbe48,0xbdc93f7b,0x3dc93f6d,0xbf7f3ec4,0xbf46bec4,0x3f22bf6d,
0x3ef1bf7b,0x3f623e48,0x3e953f55,0xbf753f0e,0xbec43f80,0xbf6d8000,0x3ec4bf80,0x3f6d8000,0x3f6dbf35,0x3ec43f35,0xbf6d3f35,0xbec4bf35,
0xbf6d0000,0x3ec4bf80,0x3f6d0000,0xbec43f80,0x3ec43f35,0xbf6d3f35,0xbec4bf35,0x3f6dbf35,0xbf620000,0x3ef1bf80,0x3e953f35,0xbf753f35,
0x3dc93f55,0xbf7f3f0e,0x3f22bf7b,0x3f463e48,0x3f46bf6d,0x3f223ec4,0xbf7f3ec4,0x3dc9bf6d,0xbf753e48,0x3e95bf7b,0x3ef13f0e,0xbf623f55,
0x3f0ebf80,0x3f558000,0xbf550000,0x3f0ebf80,0xbf7b3ec4,0x3e48bf6d,0xbe483f6d,0xbf7b3ec4,0x3e483f35,0xbf7b3f35,0x3f7bbf35,0x3e483f35,
0x3f55bf6d,0x3f0e3ec4,0xbf0ebec4,0x3f55bf6d,0x3f460000,0xbf223f80,0x3f7fbf35,0x3dc93f35,0x3ef1bf7b,0x3f62be48,0xbe95bf0e,0x3f75bf55,
0xbf753ec4,0x3e95bf6d,0xbf623f6d,0xbef1bec4,0xbdc93f55,0xbf7f3f0e,0x3f223e48,0xbf463f7b,0xbf353f80,0xbf358000,0xbf353f80,0xbf358000,
0x3f350000,0xbf353f80,0x3f350000,0xbf353f80,0x3f35bf80,0x3f358000,0x3f35bf80,0x3f358000,0xbf350000,0x3f35bf80,0xbf350000,0x3f35bf80,
0xbf220000,0x3f46bf80,0x3dc9bf35,0x3f7fbf35,0xbf623f7b,0xbef1be48,0xbf753f0e,0x3e95bf55,0x3e953ec4,0xbf753f6d,0xbef13f6d,0xbf623ec4,
0x3f7fbf55,0x3dc93f0e,0x3f46be48,0xbf223f7b,0x3f55bf80,0x3f0e8000,0x3f0e0000,0xbf553f80,0xbe48bec4,0x3f7bbf6d,0x3f7bbf6d,0x3e483ec4,
0xbf7b3f35,0x3e48bf35,0x3e48bf35,0x3f7bbf35,0xbf0e3f6d,0xbf553ec4,0xbf553ec4,0x3f0ebf6d,0x3ef10000,0xbf623f80,0xbf753f35,0x3e95bf35,
0x3f7fbf55,0xbdc93f0e,0xbf463f7b,0xbf223e48,0x3f22bf6d,0x3f46bec4,0x3dc93ec4,0xbf7f3f6d,0xbe95be48,0x3f75bf7b,0x3f62bf0e,0xbef13f55,
0xbf6d3f80,0xbec48000,0x3f6dbf80,0x3ec48000,0xbec43f35,0xbf6d3f35,0x3ec4bf35,0x3f6dbf35,0x3ec40000,0xbf6d3f80,0xbec40000,0x3f6dbf80,
0x3f6dbf35,0xbec43f35,0xbf6d3f35,0x3ec4bf35,0xbe950000,0x3f75bf80,0xbef13f35,0xbf623f35,0xbf463f0e,0x3f22bf55,0x3dc93e48,0xbf7f3f7b,
0xbf7f3f6d,0x3dc9bec4,0x3f22bec4,0xbf463f6d,0xbf623f7b,0xbef13e48,0x3f75bf55,0xbe953f0e,0x3f7bbf80,0x3e488000,0xbe480000,0x3f7bbf80,
0x3f55bf6d,0x3f0ebec4,0xbf0e3ec4,0x3f55bf6d,0x3f0ebf35,0x3f55bf35,0xbf553f35,0x3f0ebf35,0x3e48bec4,0x3f7bbf6d,0xbf7b3f6d,0x3e48bec4,
0x3dc90000,0xbf7f3f80,0x3f46bf35,0xbf223f35,0x3e95be48,0xbf753f7b,0x3f62bf55,0xbef13f0e,0x3ef1bec4,0xbf623f6d,0x3f75bf6d,0xbe953ec4,
0x3f22bf0e,0xbf463f55,0x3f7fbf7b,0xbdc93e48,0x3f803f80,0xbf803f80,0x3f803f80,0xbf803f80,0x3f803f80,0xbf803f80,0x3f803f80,0xbf803f80,
0x3f803f80,0xbf803f80,0x3f803f80,0xbf803f80,0x3f803f80,0xbf803f80,0x3f803f80,0xbf803f80,0xbf7fbf80,0x3dc98000,0xbf22bf35,0x3f463f35,
0xbf75bf7b,0x3e953e48,0xbef1bf0e,0x3f623f55,0xbf62bf6d,0x3ef13ec4,0xbe95bec4,0x3f753f6d,0xbf46bf55,0x3f223f0e,0xbdc9be48,0x3f7f3f7b,
0x3f7b3f80,0xbe488000,0xbe480000,0xbf7bbf80,0x3f553f6d,0xbf0ebec4,0xbf0ebec4,0xbf55bf6d,0x3f0e3f35,0xbf55bf35,0xbf55bf35,0xbf0ebf35,
0x3e483ec4,0xbf7bbf6d,0xbf7bbf6d,0xbe48bec4,0xbf75bf80,0x3e958000,0x3f623f35,0x3ef13f35,0xbf22bf55,0x3f463f0e,0x3f7f3f7b,0xbdc93e48,
0xbdc9bec4,0x3f7f3f6d,0x3f463f6d,0xbf22bec4,0x3ef13e48,0x3f623f7b,0x3e953f0e,0xbf75bf55,0x3f6d3f80,0xbec48000,0xbf6dbf80,0x3ec48000,
0x3ec43f35,0xbf6dbf35,0xbec4bf35,0x3f6d3f35,0xbec40000,0xbf6dbf80,0x3ec40000,0x3f6d3f80,0xbf6dbf35,0xbec4bf35,0x3f6d3f35,0x3ec43f35,
0xbf62bf80,0x3ef18000,0x3e953f35,0xbf75bf35,0xbdc9bf0e,0x3f7f3f55,0xbf22be48,0xbf46bf7b,0x3f463ec4,0x3f223f6d,0xbf7fbf6d,0x3dc9bec4,
0x3f753f7b,0xbe953e48,0xbef1bf55,0x3f623f0e,0x3f553f80,0xbf0e8000,0x3f0e0000,0x3f553f80,0xbe483ec4,0xbf7bbf6d,0x3f7b3f6d,0xbe483ec4,
0xbf7bbf35,0xbe48bf35,0x3e483f35,0xbf7bbf35,0xbf0ebf6d,0x3f553ec4,0xbf55bec4,0xbf0ebf6d,0xbf46bf80,0x3f228000,0xbf7fbf35,0xbdc9bf35,
0x3ef1be48,0x3f623f7b,0xbe95bf55,0x3f753f0e,0x3f753f6d,0xbe953ec4,0x3f623ec4,0x3ef13f6d,0xbdc93f0e,0xbf7fbf55,0x3f223f7b,0xbf46be48,
0x3f353f80,0xbf358000,0x3f353f80,0xbf358000,0xbf350000,0xbf35bf80,0xbf350000,0xbf35bf80,0xbf35bf80,0x3f358000,0xbf35bf80,0x3f358000,
0x3f350000,0x3f353f80,0x3f350000,0x3f353f80,0xbf22bf80,0x3f468000,0x3dc9bf35,0x3f7f3f35,0x3f623e48,0x3ef13f7b,0x3f753f55,0xbe953f0e,
0x3e953f6d,0xbf75bec4,0xbef13ec4,0xbf62bf6d,0xbf7fbf0e,0xbdc9bf55,0xbf46bf7b,0x3f22be48,0x3f0e3f80,0xbf558000,0xbf550000,0xbf0ebf80,
0xbf7bbec4,0xbe48bf6d,0xbe48bf6d,0x3f7b3ec4,0x3e48bf35,0x3f7b3f35,0x3f7b3f35,0xbe483f35,0x3f553f6d,0xbf0e3ec4,0xbf0e3ec4,0xbf55bf6d,
0xbef1bf80,0x3f628000,0x3f753f35,0xbe953f35,0x3f7f3f0e,0xbdc93f55,0xbf463e48,0xbf22bf7b,0xbf223ec4,0xbf46bf6d,0xbdc9bf6d,0x3f7f3ec4,
0xbe95bf7b,0x3f753e48,0x3f623f55,0xbef13f0e,0x3ec43f80,0xbf6d8000,0xbec4bf80,0x3f6d8000,0xbf6dbf35,0x3ec4bf35,0x3f6d3f35,0xbec43f35,
0x3f6d0000,0x3ec43f80,0xbf6d0000,0xbec4bf80,0xbec43f35,0xbf6dbf35,0x3ec4bf35,0x3f6d3f35,0xbe95bf80,0x3f758000,0xbef13f35,0xbf62bf35,
0x3f463f55,0xbf223f0e,0xbdc9bf7b,0x3f7f3e48,0xbf7fbec4,0x3dc9bf6d,0x3f223f6d,0xbf463ec4,0x3f62be48,0x3ef13f7b,0xbf75bf0e,0x3e95bf55,
0x3e483f80,0xbf7b8000,0x3f7b0000,0x3e483f80,0xbf0ebf6d,0x3f55bec4,0xbf553ec4,0xbf0ebf6d,0x3f553f35,0xbf0e3f35,0x3f0ebf35,0x3f553f35,
0xbf7bbec4,0x3e48bf6d,0xbe483f6d,0xbf7bbec4,0xbdc9bf80,0x3f7f8000,0xbf46bf35,0x3f22bf35,0x3e953f7b,0xbf753e48,0x3f623f0e,0xbef13f55,
0xbef1bf6d,0x3f62bec4,0xbf75bec4,0x3e95bf6d,0x3f223f55,0xbf463f0e,0x3f7f3e48,0xbdc93f7b,0x3f80,0xbf808000,0x3f80,0xbf808000,
0xbf80,0x3f808000,0xbf80,0x3f808000,0x3f80,0xbf808000,0x3f80,0xbf808000,0xbf80,0x3f808000,0xbf80,0x3f808000,
0x3dc9bf80,0x3f7f8000,0x3f46bf35,0x3f223f35,0xbe953f7b,0xbf75be48,0xbf623f0e,0xbef1bf55,0x3ef1bf6d,0x3f623ec4,0x3f75bec4,0x3e953f6d,
0xbf223f55,0xbf46bf0e,0xbf7f3e48,0xbdc9bf7b,0xbe483f80,0xbf7b8000,0xbf7b0000,0x3e48bf80,0x3f0ebf6d,0x3f553ec4,0x3f553ec4,0xbf0e3f6d,
0xbf553f35,0xbf0ebf35,0xbf0ebf35,0x3f55bf35,0x3f7bbec4,0x3e483f6d,0x3e483f6d,0xbf7b3ec4,0x3e95bf80,0x3f758000,0x3ef13f35,0xbf623f35,
0xbf463f55,0xbf22bf0e,0x3dc9bf7b,0x3f7fbe48,0x3f7fbec4,0x3dc93f6d,0xbf223f6d,0xbf46bec4,0xbf62be48,0x3ef1bf7b,0x3f75bf0e,0x3e953f55,
0xbec43f80,0xbf6d8000,0x3ec4bf80,0x3f6d8000,0x3f6dbf35,0x3ec43f35,0xbf6d3f35,0xbec4bf35,0xbf6d0000,0x3ec4bf80,0x3f6d0000,0xbec43f80,
0x3ec43f35,0xbf6d3f35,0xbec4bf35,0x3f6dbf35,0x3ef1bf80,0x3f628000,0xbf753f35,0xbe95bf35,0xbf7f3f0e,0xbdc9bf55,0x3f463e48,0xbf223f7b,
0x3f223ec4,0xbf463f6d,0x3dc9bf6d,0x3f7fbec4,0x3e95bf7b,0x3f75be48,0xbf623f55,0xbef1bf0e,0xbf0e3f80,0xbf558000,0x3f550000,0xbf0e3f80,
0x3f7bbec4,0xbe483f6d,0x3e48bf6d,0x3f7bbec4,0xbe48bf35,0x3f7bbf35,0xbf7b3f35,0xbe48bf35,0xbf553f6d,0xbf0ebec4,0x3f0e3ec4,0xbf553f6d,
0x3f22bf80,0x3f468000,0xbdc9bf35,0x3f7fbf35,0xbf623e48,0x3ef1bf7b,0xbf753f55,0xbe95bf0e,0xbe953f6d,0xbf753ec4,0x3ef13ec4,0xbf623f6d,
0x3f7fbf0e,0xbdc93f55,0x3f46bf7b,0x3f223e48,0xbf353f80,0xbf358000,0xbf353f80,0xbf358000,0x3f350000,0xbf353f80,0x3f350000,0xbf353f80,
0x3f35bf80,0x3f358000,0x3f35bf80,0x3f358000,0xbf350000,0x3f35bf80,0xbf350000,0x3f35bf80,0x3f46bf80,0x3f228000,0x3f7fbf35,0xbdc93f35,
0xbef1be48,0x3f62bf7b,0x3e95bf55,0x3f75bf0e,0xbf753f6d,0xbe95bec4,0xbf623ec4,0x3ef1bf6d,0x3dc93f0e,0xbf7f3f55,0xbf223f7b,0xbf463e48,
0xbf553f80,0xbf0e8000,0xbf0e0000,0x3f55bf80,0x3e483ec4,0xbf7b3f6d,0xbf7b3f6d,0xbe48bec4,0x3f7bbf35,0xbe483f35,0xbe483f35,0xbf7b3f35,
0x3f0ebf6d,0x3f55bec4,0x3f55bec4,0xbf0e3f6d,0x3f62bf80,0x3ef18000,0xbe953f35,0xbf753f35,0x3dc9bf0e,0x3f7fbf55,0x3f22be48,0xbf463f7b,
0xbf463ec4,0x3f22bf6d,0x3f7fbf6d,0x3dc93ec4,0xbf753f7b,0xbe95be48,0x3ef1bf55,0x3f62bf0e,0xbf6d3f80,0xbec48000,0x3f6dbf80,0x3ec48000,
0xbec43f35,0xbf6d3f35,0x3ec4bf35,0x3f6dbf35,0x3ec40000,0xbf6d3f80,0xbec40000,0x3f6dbf80,0x3f6dbf35,0xbec43f35,0xbf6d3f35,0x3ec4bf35,
0x3f75bf80,0x3e958000,0xbf623f35,0x3ef1bf35,0x3f22bf55,0x3f46bf0e,0xbf7f3f7b,0xbdc9be48,0x3dc9bec4,0x3f7fbf6d,0xbf463f6d,0xbf223ec4,
0xbef13e48,0x3f62bf7b,0xbe953f0e,0xbf753f55,0xbf7b3f80,0xbe488000,0x3e480000,0xbf7b3f80,0xbf553f6d,0xbf0e3ec4,0x3f0ebec4,0xbf553f6d,
0xbf0e3f35,0xbf553f35,0x3f55bf35,0xbf0e3f35,0xbe483ec4,0xbf7b3f6d,0x3f7bbf6d,0xbe483ec4,0x3f7fbf80,0x3dc98000,0x3f22bf35,0x3f46bf35,
0x3f75bf7b,0x3e95be48,0x3ef1bf0e,0x3f62bf55,0x3f62bf6d,0x3ef1bec4,0x3e95bec4,0x3f75bf6d,0x3f46bf55,0x3f22bf0e,0x3dc9be48,0x3f7fbf7b,
0x3f803f80,0xbf803f80,0x3f803f80,0xbf803f80,0x3f803f80,0xbf803f80,0x3f803f80,0xbf803f80,0x3f803f80,0xbf803f80,0x3f803f80,0xbf803f80,
0x3f803f80,0xbf803f80,0x3f803f80,0xbf803f80,0x3dc90000,0x3f7f3f80,0x3f463f35,0x3f223f35,0x3e953e48,0x3f753f7b,0x3f623f55,0x3ef13f0e,
0x3ef13ec4,0x3f623f6d,0x3f753f6d,0x3e953ec4,0x3f223f0e,0x3f463f55,0x3f7f3f7b,0x3dc93e48,0xbf7bbf80,0x3e488000,0x3e480000,0x3f7b3f80,
0xbf55bf6d,0x3f0e3ec4,0x3f0e3ec4,0x3f553f6d,0xbf0ebf35,0x3f553f35,0x3f553f35,0x3f0e3f35,0xbe48bec4,0x3f7b3f6d,0x3f7b3f6d,0x3e483ec4,
0xbe950000,0xbf75bf80,0xbef1bf35,0x3f623f35,0xbf46bf0e,0xbf22bf55,0x3dc9be48,0x3f7f3f7b,0xbf7fbf6d,0xbdc9bec4,0x3f223ec4,0x3f463f6d,
0xbf62bf7b,0x3ef13e48,0x3f753f55,0x3e953f0e,0x3f6d3f80,0xbec48000,0xbf6dbf80,0x3ec48000,0x3ec43f35,0xbf6dbf35,0xbec4bf35,0x3f6d3f35,
0xbec40000,0xbf6dbf80,0x3ec40000,0x3f6d3f80,0xbf6dbf35,0xbec4bf35,0x3f6d3f35,0x3ec43f35,0x3ef10000,0x3f623f80,0xbf75bf35,0xbe95bf35,
0x3f7f3f55,0x3dc93f0e,0xbf46bf7b,0x3f223e48,0x3f223f6d,0xbf46bec4,0x3dc9bec4,0x3f7f3f6d,0xbe953e48,0xbf75bf7b,0x3f623f0e,0x3ef13f55,
0xbf55bf80,0x3f0e8000,0xbf0e0000,0xbf55bf80,0x3e48bec4,0x3f7b3f6d,0xbf7bbf6d,0x3e48bec4,0x3f7b3f35,0x3e483f35,0xbe48bf35,0x3f7b3f35,
0x3f0e3f6d,0xbf55bec4,0x3f553ec4,0x3f0e3f6d,0xbf220000,0xbf46bf80,0x3dc93f35,0xbf7fbf35,0xbf62bf7b,0x3ef1be48,0xbf75bf0e,0xbe95bf55,
0x3e95bec4,0x3f753f6d,0xbef1bf6d,0x3f623ec4,0x3f7f3f55,0xbdc93f0e,0x3f463e48,0x3f223f7b,0x3f353f80,0xbf358000,0x3f353f80,0xbf358000,
0xbf350000,0xbf35bf80,0xbf350000,0xbf35bf80,0xbf35bf80,0x3f358000,0xbf35bf80,0x3f358000,0x3f350000,0x3f353f80,0x3f350000,0x3f353f80,
0x3f460000,0x3f223f80,0x3f7f3f35,0xbdc93f35,0x3ef13f7b,0xbf62be48,0xbe953f0e,0xbf75bf55,0xbf75bec4,0xbe95bf6d,0xbf62bf6d,0x3ef1bec4,
0xbdc9bf55,0x3f7f3f0e,0x3f22be48,0x3f463f7b,0xbf0ebf80,0x3f558000,0x3f550000,0x3f0e3f80,0x3f7b3ec4,0x3e483f6d,0x3e483f6d,0xbf7bbec4,
0xbe483f35,0xbf7bbf35,0xbf7bbf35,0x3e48bf35,0xbf55bf6d,0x3f0ebec4,0x3f0ebec4,0x3f553f6d,0xbf620000,0xbef1bf80,0x3e95bf35,0x3f753f35,
0x3dc9bf55,0x3f7f3f0e,0x3f223f7b,0xbf463e48,0x3f463f6d,0xbf223ec4,0xbf7fbec4,0xbdc9bf6d,0xbf75be48,0xbe95bf7b,0x3ef1bf0e,0x3f623f55,
0x3ec43f80,0xbf6d8000,0xbec4bf80,0x3f6d8000,0xbf6dbf35,0x3ec4bf35,0x3f6d3f35,0xbec43f35,0x3f6d0000,0x3ec43f80,0xbf6d0000,0xbec4bf80,
0xbec43f35,0xbf6dbf35,0x3ec4bf35,0x3f6d3f35,0x3f750000,0x3e953f80,0xbf62bf35,0x3ef1bf35,0xbf223f0e,0xbf46bf55,0x3f7f3e48,0x3dc93f7b,
0x3dc9bf6d,0x3f7f3ec4,0xbf463ec4,0xbf22bf6d,0x3ef13f7b,0xbf623e48,0x3e95bf55,0x3f753f0e,0xbe48bf80,0x3f7b8000,0xbf7b0000,0xbe48bf80,
0x3f0e3f6d,0xbf553ec4,0x3f55bec4,0x3f0e3f6d,0xbf55bf35,0x3f0ebf35,0xbf0e3f35,0xbf55bf35,0x3f7b3ec4,0xbe483f6d,0x3e48bf6d,0x3f7b3ec4,
0xbf7f0000,0xbdc9bf80,0xbf223f35,0xbf46bf35,0x3f75be48,0x3e953f7b,0x3ef1bf55,0x3f623f0e,0xbf623ec4,0xbef1bf6d,0xbe953f6d,0xbf75bec4,
0x3f46bf0e,0x3f223f55,0x3dc9bf7b,0x3f7f3e48,0x3f80,0xbf808000,0x3f80,0xbf808000,0xbf80,0x3f808000,0xbf80,0x3f808000,
0x3f80,0xbf808000,0x3f80,0xbf808000,0xbf80,0x3f808000,0xbf80,0x3f808000,0x3f7f0000,0xbdc93f80,0x3f223f35,0xbf463f35,
0xbf75be48,0x3e95bf7b,0xbef1bf55,0x3f62bf0e,0x3f623ec4,0xbef13f6d,0x3e953f6d,0xbf753ec4,0xbf46bf0e,0x3f22bf55,0xbdc9bf7b,0x3f7fbe48,
0x3e48bf80,0x3f7b8000,0x3f7b0000,0xbe483f80,0xbf0e3f6d,0xbf55bec4,0xbf55bec4,0x3f0ebf6d,0x3f55bf35,0x3f0e3f35,0x3f0e3f35,0xbf553f35,
0xbf7b3ec4,0xbe48bf6d,0xbe48bf6d,0x3f7bbec4,0xbf750000,0x3e95bf80,0x3f62bf35,0x3ef13f35,0x3f223f0e,0xbf463f55,0xbf7f3e48,0x3dc9bf7b,
0xbdc9bf6d,0x3f7fbec4,0x3f463ec4,0xbf223f6d,0xbef13f7b,0xbf62be48,0xbe95bf55,0x3f75bf0e,0xbec43f80,0xbf6d8000,0x3ec4bf80,0x3f6d8000,
0x3f6dbf35,0x3ec43f35,0xbf6d3f35,0xbec4bf35,0xbf6d0000,0x3ec4bf80,0x3f6d0000,0xbec43f80,0x3ec43f35,0xbf6d3f35,0xbec4bf35,0x3f6dbf35,
0x3f620000,0xbef13f80,0xbe95bf35,0x3f75bf35,0xbdc9bf55,0x3f7fbf0e,0xbf223f7b,0xbf46be48,0xbf463f6d,0xbf22bec4,0x3f7fbec4,0xbdc93f6d,
0x3f75be48,0xbe953f7b,0xbef1bf0e,0x3f62bf55,0x3f0ebf80,0x3f558000,0xbf550000,0x3f0ebf80,0xbf7b3ec4,0x3e48bf6d,0xbe483f6d,0xbf7b3ec4,
0x3e483f35,0xbf7b3f35,0x3f7bbf35,0x3e483f35,0x3f55bf6d,0x3f0e3ec4,0xbf0ebec4,0x3f55bf6d,0xbf460000,0x3f22bf80,0xbf7f3f35,0xbdc9bf35,
0xbef13f7b,0xbf623e48,0x3e953f0e,0xbf753f55,0x3f75bec4,0xbe953f6d,0x3f62bf6d,0x3ef13ec4,0x3dc9bf55,0x3f7fbf0e,0xbf22be48,0x3f46bf7b,
0xbf353f80,0xbf358000,0xbf353f80,0xbf358000,0x3f350000,0xbf353f80,0x3f350000,0xbf353f80,0x3f35bf80,0x3f358000,0x3f35bf80,0x3f358000,
0xbf350000,0x3f35bf80,0xbf350000,0x3f35bf80,0x3f220000,0xbf463f80,0xbdc93f35,0xbf7f3f35,0x3f62bf7b,0x3ef13e48,0x3f75bf0e,0xbe953f55,
0xbe95bec4,0x3f75bf6d,0x3ef1bf6d,0x3f62bec4,0xbf7f3f55,0xbdc9bf0e,0xbf463e48,0x3f22bf7b,0x3f55bf80,0x3f0e8000,0x3f0e0000,0xbf553f80,
0xbe48bec4,0x3f7bbf6d,0x3f7bbf6d,0x3e483ec4,0xbf7b3f35,0x3e48bf35,0x3e48bf35,0x3f7bbf35,0xbf0e3f6d,0xbf553ec4,0xbf553ec4,0x3f0ebf6d,
0xbef10000,0x3f62bf80,0x3f75bf35,0xbe953f35,0xbf7f3f55,0x3dc9bf0e,0x3f46bf7b,0x3f22be48,0xbf223f6d,0xbf463ec4,0xbdc9bec4,0x3f7fbf6d,
0x3e953e48,0xbf753f7b,0xbf623f0e,0x3ef1bf55,0xbf6d3f80,0xbec48000,0x3f6dbf80,0x3ec48000,0xbec43f35,0xbf6d3f35,0x3ec4bf35,0x3f6dbf35,
0x3ec40000,0xbf6d3f80,0xbec40000,0x3f6dbf80,0x3f6dbf35,0xbec43f35,0xbf6d3f35,0x3ec4bf35,0x3e950000,0xbf753f80,0x3ef1bf35,0x3f62bf35,
0x3f46bf0e,0xbf223f55,0xbdc9be48,0x3f7fbf7b,0x3f7fbf6d,0xbdc93ec4,0xbf223ec4,0x3f46bf6d,0x3f62bf7b,0x3ef1be48,0xbf753f55,0x3e95bf0e,
0x3f7bbf80,0x3e488000,0xbe480000,0x3f7bbf80,0x3f55bf6d,0x3f0ebec4,0xbf0e3ec4,0x3f55bf6d,0x3f0ebf35,0x3f55bf35,0xbf553f35,0x3f0ebf35,
0x3e48bec4,0x3f7bbf6d,0xbf7b3f6d,0x3e48bec4,0xbdc90000,0x3f7fbf80,0xbf463f35,0x3f22bf35,0xbe953e48,0x3f75bf7b,0xbf623f55,0x3ef1bf0e,
0xbef13ec4,0x3f62bf6d,0xbf753f6d,0x3e95bec4,0xbf223f0e,0x3f46bf55,0xbf7f3f7b,0x3dc9be48,0x3f803f80,0x3f803f80,0x3f803f80,0x3f803f80,
0x3f803f80,0x3f803f80,0x3f803f80,0x3f803f80,0x3f803f80,0x3f803f80,0x3f803f80,0x3f803f80,0x3f803f80,0x3f803f80,0x3f803f80,0x3f803f80,
0x0,0x0,0x0,0x0,0x0,0x0,0x0,0x0,0x0,0x0,0x0,0x0,
0x0,0x0,0x0,0x0,0xbe480000,0xbf0ebec4,0xbf55bf35,0xbf7bbf6d,0x3f7b3f80,0x3f553f6d,0x3f0e3f35,0x3e483ec4,
0x3e480000,0x3f0e3ec4,0x3f553f35,0x3f7b3f6d,0xbf7bbf80,0xbf55bf6d,0xbf0ebf35,0xbe48bec4,0x3f7b3f80,0x3f553f6d,0x3f0e3f35,0x3e483ec4,
0x3e480000,0x3f0e3ec4,0x3f553f35,0x3f7b3f6d,0xbf7bbf80,0xbf55bf6d,0xbf0ebf35,0xbe48bec4,0xbe480000,0xbf0ebec4,0xbf55bf35,0xbf7bbf6d,
0x3f6d3f80,0x3ec43f35,0xbec40000,0xbf6dbf35,0xbf6dbf80,0xbec4bf35,0x3ec40000,0x3f6d3f35,0x3f6d3f80,0x3ec43f35,0xbec40000,0xbf6dbf35,
0xbf6dbf80,0xbec4bf35,0x3ec40000,0x3f6d3f35,0x3ec40000,0x3f6d3f35,0x3f6d3f80,0x3ec43f35,0xbec40000,0xbf6dbf35,0xbf6dbf80,0xbec4bf35,
0x3ec40000,0x3f6d3f35,0x3f6d3f80,0x3ec43f35,0xbec40000,0xbf6dbf35,0xbf6dbf80,0xbec4bf35,0xbf0e0000,0xbf7bbf6d,0xbe48bf35,0x3f553ec4,
0xbf55bf80,0x3e48bec4,0x3f7b3f35,0x3f0e3f6d,0x3f0e0000,0x3f7b3f6d,0x3e483f35,0xbf55bec4,0x3f553f80,0xbe483ec4,0xbf7bbf35,0xbf0ebf6d,
0x3f553f80,0xbe483ec4,0xbf7bbf35,0xbf0ebf6d,0xbf0e0000,0xbf7bbf6d,0xbe48bf35,0x3f553ec4,0xbf55bf80,0x3e48bec4,0x3f7b3f35,0x3f0e3f6d,
0x3f0e0000,0x3f7b3f6d,0x3e483f35,0xbf55bec4,0x3f350000,0x3f353f80,0xbf350000,0xbf35bf80,0x3f350000,0x3f353f80,0xbf350000,0xbf35bf80,
0x3f350000,0x3f353f80,0xbf350000,0xbf35bf80,0x3f350000,0x3f353f80,0xbf350000,0xbf35bf80,0x3f353f80,0xbf350000,0xbf35bf80,0x3f350000,
0x3f353f80,0xbf350000,0xbf35bf80,0x3f350000,0x3f353f80,0xbf350000,0xbf35bf80,0x3f350000,0x3f353f80,0xbf350000,0xbf35bf80,0x3f350000,
0x3f0e3f80,0xbf7bbec4,0x3e48bf35,0x3f553f6d,0x3f550000,0x3e483f6d,0xbf7bbf35,0x3f0ebec4,0xbf0ebf80,0x3f7b3ec4,0xbe483f35,0xbf55bf6d,
0xbf550000,0xbe48bf6d,0x3f7b3f35,0xbf0e3ec4,0xbf550000,0xbe48bf6d,0x3f7b3f35,0xbf0e3ec4,0x3f0e3f80,0xbf7bbec4,0x3e48bf35,0x3f553f6d,
0x3f550000,0x3e483f6d,0xbf7bbf35,0x3f0ebec4,0xbf0ebf80,0x3f7b3ec4,0xbe483f35,0xbf55bf6d,0x3f6d0000,0xbec43f35,0xbec4bf80,0x3f6d3f35,
0xbf6d0000,0x3ec4bf35,0x3ec43f80,0xbf6dbf35,0x3f6d0000,0xbec43f35,0xbec4bf80,0x3f6d3f35,0xbf6d0000,0x3ec4bf35,0x3ec43f80,0xbf6dbf35,
0x3ec43f80,0xbf6dbf35,0x3f6d0000,0xbec43f35,0xbec4bf80,0x3f6d3f35,0xbf6d0000,0x3ec4bf35,0x3ec43f80,0xbf6dbf35,0x3f6d0000,0xbec43f35,
0xbec4bf80,0x3f6d3f35,0xbf6d0000,0x3ec4bf35,0x3e483f80,0xbf0ebf6d,0x3f553f35,0xbf7bbec4,0xbf7b0000,0x3f55bec4,0xbf0e3f35,0x3e48bf6d,
0xbe48bf80,0x3f0e3f6d,0xbf55bf35,0x3f7b3ec4,0x3f7b0000,0xbf553ec4,0x3f0ebf35,0xbe483f6d,0xbf7b0000,0x3f55bec4,0xbf0e3f35,0x3e48bf6d,
0xbe48bf80,0x3f0e3f6d,0xbf55bf35,0x3f7b3ec4,0x3f7b0000,0xbf553ec4,0x3f0ebf35,0xbe483f6d,0x3e483f80,0xbf0ebf6d,0x3f553f35,0xbf7bbec4,
0x3f80,0xbf80,0x3f80,0xbf80,0x3f80,0xbf80,0x3f80,0xbf80,0x3f80,0xbf80,0x3f80,0xbf80,
0x3f80,0xbf80,0x3f80,0xbf80,0x3f800000,0xbf800000,0x3f800000,0xbf800000,0x3f800000,0xbf800000,0x3f800000,0xbf800000,
0x3f800000,0xbf800000,0x3f800000,0xbf800000,0x3f800000,0xbf800000,0x3f800000,0xbf800000,0xbf7b0000,0x3f553ec4,0xbf0ebf35,0x3e483f6d,
0xbe483f80,0x3f0ebf6d,0xbf553f35,0x3f7bbec4,0x3f7b0000,0xbf55bec4,0x3f0e3f35,0xbe48bf6d,0x3e48bf80,0xbf0e3f6d,0x3f55bf35,0xbf7b3ec4,
0xbe483f80,0x3f0ebf6d,0xbf553f35,0x3f7bbec4,0x3f7b0000,0xbf55bec4,0x3f0e3f35,0xbe48bf6d,0x3e48bf80,0xbf0e3f6d,0x3f55bf35,0xbf7b3ec4,
0xbf7b0000,0x3f553ec4,0xbf0ebf35,0x3e483f6d,0xbec43f80,0x3f6dbf35,0xbf6d0000,0x3ec43f35,0x3ec4bf80,0xbf6d3f35,0x3f6d0000,0xbec4bf35,
0xbec43f80,0x3f6dbf35,0xbf6d0000,0x3ec43f35,0x3ec4bf80,0xbf6d3f35,0x3f6d0000,0xbec4bf35,0x3f6d0000,0xbec4bf35,0xbec43f80,0x3f6dbf35,
0xbf6d0000,0x3ec43f35,0x3ec4bf80,0xbf6d3f35,0x3f6d0000,0xbec4bf35,0xbec43f80,0x3f6dbf35,0xbf6d0000,0x3ec43f35,0x3ec4bf80,0xbf6d3f35,
0xbf550000,0xbe483f6d,0x3f7bbf35,0xbf0ebec4,0x3f0ebf80,0xbf7b3ec4,0x3e483f35,0x3f55bf6d,0x3f550000,0x3e48bf6d,0xbf7b3f35,0x3f0e3ec4,
0xbf0e3f80,0x3f7bbec4,0xbe48bf35,0xbf553f6d,0xbf0e3f80,0x3f7bbec4,0xbe48bf35,0xbf553f6d,0xbf550000,0xbe483f6d,0x3f7bbf35,0xbf0ebec4,
0x3f0ebf80,0xbf7b3ec4,0x3e483f35,0x3f55bf6d,0x3f550000,0x3e48bf6d,0xbf7b3f35,0x3f0e3ec4,0x3f350000,0x3f35bf80,0xbf350000,0xbf353f80,
0x3f350000,0x3f35bf80,0xbf350000,0xbf353f80,0x3f350000,0x3f35bf80,0xbf350000,0xbf353f80,0x3f350000,0x3f35bf80,0xbf350000,0xbf353f80,
0xbf353f80,0x3f350000,0x3f35bf80,0xbf350000,0xbf353f80,0x3f350000,0x3f35bf80,0xbf350000,0xbf353f80,0x3f350000,0x3f35bf80,0xbf350000,
0xbf353f80,0x3f350000,0x3f35bf80,0xbf350000,0xbf553f80,0x3e483ec4,0x3f7bbf35,0x3f0ebf6d,0x3f0e0000,0x3f7bbf6d,0x3e48bf35,0xbf553ec4,
0x3f55bf80,0xbe48bec4,0xbf7b3f35,0xbf0e3f6d,0xbf0e0000,0xbf7b3f6d,0xbe483f35,0x3f55bec4,0xbf0e0000,0xbf7b3f6d,0xbe483f35,0x3f55bec4,
0xbf553f80,0x3e483ec4,0x3f7bbf35,0x3f0ebf6d,0x3f0e0000,0x3f7bbf6d,0x3e48bf35,0xbf553ec4,0x3f55bf80,0xbe48bec4,0xbf7b3f35,0xbf0e3f6d,
0x3ec40000,0x3f6dbf35,0x3f6dbf80,0x3ec4bf35,0xbec40000,0xbf6d3f35,0xbf6d3f80,0xbec43f35,0x3ec40000,0x3f6dbf35,0x3f6dbf80,0x3ec4bf35,
0xbec40000,0xbf6d3f35,0xbf6d3f80,0xbec43f35,0xbf6d3f80,0xbec43f35,0x3ec40000,0x3f6dbf35,0x3f6dbf80,0x3ec4bf35,0xbec40000,0xbf6d3f35,
0xbf6d3f80,0xbec43f35,0x3ec40000,0x3f6dbf35,0x3f6dbf80,0x3ec4bf35,0xbec40000,0xbf6d3f35,0xbf7b3f80,0xbf553f6d,0xbf0e3f35,0xbe483ec4,
0xbe480000,0xbf0e3ec4,0xbf553f35,0xbf7b3f6d,0x3f7bbf80,0x3f55bf6d,0x3f0ebf35,0x3e48bec4,0x3e480000,0x3f0ebec4,0x3f55bf35,0x3f7bbf6d,
0xbe480000,0xbf0e3ec4,0xbf553f35,0xbf7b3f6d,0x3f7bbf80,0x3f55bf6d,0x3f0ebf35,0x3e48bec4,0x3e480000,0x3f0ebec4,0x3f55bf35,0x3f7bbf6d,
0xbf7b3f80,0xbf553f6d,0xbf0e3f35,0xbe483ec4,0xbf803f80,0xbf803f80,0xbf803f80,0xbf803f80,0xbf803f80,0xbf803f80,0xbf803f80,0xbf803f80,
0xbf803f80,0xbf803f80,0xbf803f80,0xbf803f80,0xbf803f80,0xbf803f80,0xbf803f80,0xbf803f80,0x0,0x0,0x0,0x0,
0x0,0x0,0x0,0x0,0x0,0x0,0x0,0x0,0x0,0x0,0x0,0x0,
0x3e480000,0x3f0ebec4,0x3f55bf35,0x3f7bbf6d,0xbf7b3f80,0xbf553f6d,0xbf0e3f35,0xbe483ec4,0xbe480000,0xbf0e3ec4,0xbf553f35,0xbf7b3f6d,
0x3f7bbf80,0x3f55bf6d,0x3f0ebf35,0x3e48bec4,0xbf7b3f80,0xbf553f6d,0xbf0e3f35,0xbe483ec4,0xbe480000,0xbf0e3ec4,0xbf553f35,0xbf7b3f6d,
0x3f7bbf80,0x3f55bf6d,0x3f0ebf35,0x3e48bec4,0x3e480000,0x3f0ebec4,0x3f55bf35,0x3f7bbf6d,0xbf6d3f80,0xbec43f35,0x3ec40000,0x3f6dbf35,
0x3f6dbf80,0x3ec4bf35,0xbec40000,0xbf6d3f35,0xbf6d3f80,0xbec43f35,0x3ec40000,0x3f6dbf35,0x3f6dbf80,0x3ec4bf35,0xbec40000,0xbf6d3f35,
0xbec40000,0xbf6d3f35,0xbf6d3f80,0xbec43f35,0x3ec40000,0x3f6dbf35,0x3f6dbf80,0x3ec4bf35,0xbec40000,0xbf6d3f35,0xbf6d3f80,0xbec43f35,
0x3ec40000,0x3f6dbf35,0x3f6dbf80,0x3ec4bf35,0x3f0e0000,0x3f7bbf6d,0x3e48bf35,0xbf553ec4,0x3f55bf80,0xbe48bec4,0xbf7b3f35,0xbf0e3f6d,
0xbf0e0000,0xbf7b3f6d,0xbe483f35,0x3f55bec4,0xbf553f80,0x3e483ec4,0x3f7bbf35,0x3f0ebf6d,0xbf553f80,0x3e483ec4,0x3f7bbf35,0x3f0ebf6d,
0x3f0e0000,0x3f7bbf6d,0x3e48bf35,0xbf553ec4,0x3f55bf80,0xbe48bec4,0xbf7b3f35,0xbf0e3f6d,0xbf0e0000,0xbf7b3f6d,0xbe483f35,0x3f55bec4,
0xbf350000,0xbf353f80,0x3f350000,0x3f35bf80,0xbf350000,0xbf353f80,0x3f350000,0x3f35bf80,0xbf350000,0xbf353f80,0x3f350000,0x3f35bf80,
0xbf350000,0xbf353f80,0x3f350000,0x3f35bf80,0xbf353f80,0x3f350000,0x3f35bf80,0xbf350000,0xbf353f80,0x3f350000,0x3f35bf80,0xbf350000,
0xbf353f80,0x3f350000,0x3f35bf80,0xbf350000,0xbf353f80,0x3f350000,0x3f35bf80,0xbf350000,0xbf0e3f80,0x3f7bbec4,0xbe48bf35,0xbf553f6d,
0xbf550000,0xbe483f6d,0x3f7bbf35,0xbf0ebec4,0x3f0ebf80,0xbf7b3ec4,0x3e483f35,0x3f55bf6d,0x3f550000,0x3e48bf6d,0xbf7b3f35,0x3f0e3ec4,
0x3f550000,0x3e48bf6d,0xbf7b3f35,0x3f0e3ec4,0xbf0e3f80,0x3f7bbec4,0xbe48bf35,0xbf553f6d,0xbf550000,0xbe483f6d,0x3f7bbf35,0xbf0ebec4,
0x3f0ebf80,0xbf7b3ec4,0x3e483f35,0x3f55bf6d,0xbf6d0000,0x3ec43f35,0x3ec4bf80,0xbf6d3f35,0x3f6d0000,0xbec4bf35,0xbec43f80,0x3f6dbf35,
0xbf6d0000,0x3ec43f35,0x3ec4bf80,0xbf6d3f35,0x3f6d0000,0xbec4bf35,0xbec43f80,0x3f6dbf35,0xbec43f80,0x3f6dbf35,0xbf6d0000,0x3ec43f35,
0x3ec4bf80,0xbf6d3f35,0x3f6d0000,0xbec4bf35,0xbec43f80,0x3f6dbf35,0xbf6d0000,0x3ec43f35,0x3ec4bf80,0xbf6d3f35,0x3f6d0000,0xbec4bf35,
0xbe483f80,0x3f0ebf6d,0xbf553f35,0x3f7bbec4,0x3f7b0000,0xbf55bec4,0x3f0e3f35,0xbe48bf6d,0x3e48bf80,0xbf0e3f6d,0x3f55bf35,0xbf7b3ec4,
0xbf7b0000,0x3f553ec4,0xbf0ebf35,0x3e483f6d,0x3f7b0000,0xbf55bec4,0x3f0e3f35,0xbe48bf6d,0x3e48bf80,0xbf0e3f6d,0x3f55bf35,0xbf7b3ec4,
0xbf7b0000,0x3f553ec4,0xbf0ebf35,0x3e483f6d,0xbe483f80,0x3f0ebf6d,0xbf553f35,0x3f7bbec4,0x3f80,0xbf80,0x3f80,0xbf80,
0x3f80,0xbf80,0x3f80,0xbf80,0x3f80,0xbf80,0x3f80,0xbf80,0x3f80,0xbf80,0x3f80,0xbf80,
0xbf800000,0x3f800000,0xbf800000,0x3f800000,0xbf800000,0x3f800000,0xbf800000,0x3f800000,0xbf800000,0x3f800000,0xbf800000,0x3f800000,
0xbf800000,0x3f800000,0xbf800000,0x3f800000,0x3f7b0000,0xbf553ec4,0x3f0ebf35,0xbe483f6d,0x3e483f80,0xbf0ebf6d,0x3f553f35,0xbf7bbec4,
0xbf7b0000,0x3f55bec4,0xbf0e3f35,0x3e48bf6d,0xbe48bf80,0x3f0e3f6d,0xbf55bf35,0x3f7b3ec4,0x3e483f80,0xbf0ebf6d,0x3f553f35,0xbf7bbec4,
0xbf7b0000,0x3f55bec4,0xbf0e3f35,0x3e48bf6d,0xbe48bf80,0x3f0e3f6d,0xbf55bf35,0x3f7b3ec4,0x3f7b0000,0xbf553ec4,0x3f0ebf35,0xbe483f6d,
0x3ec43f80,0xbf6dbf35,0x3f6d0000,0xbec43f35,0xbec4bf80,0x3f6d3f35,0xbf6d0000,0x3ec4bf35,0x3ec43f80,0xbf6dbf35,0x3f6d0000,0xbec43f35,
0xbec4bf80,0x3f6d3f35,0xbf6d0000,0x3ec4bf35,0xbf6d0000,0x3ec4bf35,0x3ec43f80,0xbf6dbf35,0x3f6d0000,0xbec43f35,0xbec4bf80,0x3f6d3f35,
0xbf6d0000,0x3ec4bf35,0x3ec43f80,0xbf6dbf35,0x3f6d0000,0xbec43f35,0xbec4bf80,0x3f6d3f35,0x3f550000,0x3e483f6d,0xbf7bbf35,0x3f0ebec4,
0xbf0ebf80,0x3f7b3ec4,0xbe483f35,0xbf55bf6d,0xbf550000,0xbe48bf6d,0x3f7b3f35,0xbf0e3ec4,0x3f0e3f80,0xbf7bbec4,0x3e48bf35,0x3f553f6d,
0x3f0e3f80,0xbf7bbec4,0x3e48bf35,0x3f553f6d,0x3f550000,0x3e483f6d,0xbf7bbf35,0x3f0ebec4,0xbf0ebf80,0x3f7b3ec4,0xbe483f35,0xbf55bf6d,
0xbf550000,0xbe48bf6d,0x3f7b3f35,0xbf0e3ec4,0xbf350000,0xbf35bf80,0x3f350000,0x3f353f80,0xbf350000,0xbf35bf80,0x3f350000,0x3f353f80,
0xbf350000,0xbf35bf80,0x3f350000,0x3f353f80,0xbf350000,0xbf35bf80,0x3f350000,0x3f353f80,0x3f353f80,0xbf350000,0xbf35bf80,0x3f350000,
0x3f353f80,0xbf350000,0xbf35bf80,0x3f350000,0x3f353f80,0xbf350000,0xbf35bf80,0x3f350000,0x3f353f80,0xbf350000,0xbf35bf80,0x3f350000,
0x3f553f80,0xbe483ec4,0xbf7bbf35,0xbf0ebf6d,0xbf0e0000,0xbf7bbf6d,0xbe48bf35,0x3f553ec4,0xbf55bf80,0x3e48bec4,0x3f7b3f35,0x3f0e3f6d,
0x3f0e0000,0x3f7b3f6d,0x3e483f35,0xbf55bec4,0x3f0e0000,0x3f7b3f6d,0x3e483f35,0xbf55bec4,0x3f553f80,0xbe483ec4,0xbf7bbf35,0xbf0ebf6d,
0xbf0e0000,0xbf7bbf6d,0xbe48bf35,0x3f553ec4,0xbf55bf80,0x3e48bec4,0x3f7b3f35,0x3f0e3f6d,0xbec40000,0xbf6dbf35,0xbf6dbf80,0xbec4bf35,
0x3ec40000,0x3f6d3f35,0x3f6d3f80,0x3ec43f35,0xbec40000,0xbf6dbf35,0xbf6dbf80,0xbec4bf35,0x3ec40000,0x3f6d3f35,0x3f6d3f80,0x3ec43f35,
0x3f6d3f80,0x3ec43f35,0xbec40000,0xbf6dbf35,0xbf6dbf80,0xbec4bf35,0x3ec40000,0x3f6d3f35,0x3f6d3f80,0x3ec43f35,0xbec40000,0xbf6dbf35,
0xbf6dbf80,0xbec4bf35,0x3ec40000,0x3f6d3f35,0x3f7b3f80,0x3f553f6d,0x3f0e3f35,0x3e483ec4,0x3e480000,0x3f0e3ec4,0x3f553f35,0x3f7b3f6d,
0xbf7bbf80,0xbf55bf6d,0xbf0ebf35,0xbe48bec4,0xbe480000,0xbf0ebec4,0xbf55bf35,0xbf7bbf6d,0x3e480000,0x3f0e3ec4,0x3f553f35,0x3f7b3f6d,
0xbf7bbf80,0xbf55bf6d,0xbf0ebf35,0xbe48bec4,0xbe480000,0xbf0ebec4,0xbf55bf35,0xbf7bbf6d,0x3f7b3f80,0x3f553f6d,0x3f0e3f35,0x3e483ec4,
0x80008000,0x80008000,0x80008000,0x80008000,0x80008000,0x80008000,0x80008000,0x80008000,0x80008000,0x80008000,0x80008000,0x80008000,
0x80008000,0x80008000,0x80008000,0x80008000,0x3f803f80,0x3f803f80,0x3f803f80,0x3f803f80,0x3f803f80,0x3f803f80,0x3f803f80,0x3f803f80,
0x3f803f80,0x3f803f80,0x3f803f80,0x3f803f80,0x3f803f80,0x3f803f80,0x3f803f80,0x3f803f80,0xbf7bbf80,0xbf55bf6d,0xbf0ebf35,0xbe48bec4,
0xbe488000,0xbf0ebec4,0xbf55bf35,0xbf7bbf6d,0x3f7b3f80,0x3f553f6d,0x3f0e3f35,0x3e483ec4,0x3e488000,0x3f0e3ec4,0x3f553f35,0x3f7b3f6d,
0xbe480000,0xbf0ebec4,0xbf55bf35,0xbf7bbf6d,0x3f7b3f80,0x3f553f6d,0x3f0e3f35,0x3e483ec4,0x3e480000,0x3f0e3ec4,0x3f553f35,0x3f7b3f6d,
0xbf7bbf80,0xbf55bf6d,0xbf0ebf35,0xbe48bec4,0xbec48000,0xbf6dbf35,0xbf6dbf80,0xbec4bf35,0x3ec48000,0x3f6d3f35,0x3f6d3f80,0x3ec43f35,
0xbec48000,0xbf6dbf35,0xbf6dbf80,0xbec4bf35,0x3ec48000,0x3f6d3f35,0x3f6d3f80,0x3ec43f35,0x3f6d3f80,0x3ec43f35,0xbec40000,0xbf6dbf35,
0xbf6dbf80,0xbec4bf35,0x3ec40000,0x3f6d3f35,0x3f6d3f80,0x3ec43f35,0xbec40000,0xbf6dbf35,0xbf6dbf80,0xbec4bf35,0x3ec40000,0x3f6d3f35,
0xbf55bf80,0x3e48bec4,0x3f7b3f35,0x3f0e3f6d,0x3f0e8000,0x3f7b3f6d,0x3e483f35,0xbf55bec4,0x3f553f80,0xbe483ec4,0xbf7bbf35,0xbf0ebf6d,
0xbf0e8000,0xbf7bbf6d,0xbe48bf35,0x3f553ec4,0xbf0e0000,0xbf7bbf6d,0xbe48bf35,0x3f553ec4,0xbf55bf80,0x3e48bec4,0x3f7b3f35,0x3f0e3f6d,
0x3f0e0000,0x3f7b3f6d,0x3e483f35,0xbf55bec4,0x3f553f80,0xbe483ec4,0xbf7bbf35,0xbf0ebf6d,0x3f353f80,0xbf350000,0xbf35bf80,0x3f350000,
0x3f353f80,0xbf350000,0xbf35bf80,0x3f350000,0x3f353f80,0xbf350000,0xbf35bf80,0x3f350000,0x3f353f80,0xbf350000,0xbf35bf80,0x3f350000,
0xbf358000,0xbf35bf80,0x3f358000,0x3f353f80,0xbf358000,0xbf35bf80,0x3f358000,0x3f353f80,0xbf358000,0xbf35bf80,0x3f358000,0x3f353f80,
0xbf358000,0xbf35bf80,0x3f358000,0x3f353f80,0xbf550000,0xbe48bf6d,0x3f7b3f35,0xbf0e3ec4,0x3f0e3f80,0xbf7bbec4,0x3e48bf35,0x3f553f6d,
0x3f550000,0x3e483f6d,0xbf7bbf35,0x3f0ebec4,0xbf0ebf80,0x3f7b3ec4,0xbe483f35,0xbf55bf6d,0xbf0ebf80,0x3f7b3ec4,0xbe483f35,0xbf55bf6d,
0xbf558000,0xbe48bf6d,0x3f7b3f35,0xbf0e3ec4,0x3f0e3f80,0xbf7bbec4,0x3e48bf35,0x3f553f6d,0x3f558000,0x3e483f6d,0xbf7bbf35,0x3f0ebec4,
0x3ec43f80,0xbf6dbf35,0x3f6d0000,0xbec43f35,0xbec4bf80,0x3f6d3f35,0xbf6d0000,0x3ec4bf35,0x3ec43f80,0xbf6dbf35,0x3f6d0000,0xbec43f35,
0xbec4bf80,0x3f6d3f35,0xbf6d0000,0x3ec4bf35,0xbf6d8000,0x3ec4bf35,0x3ec43f80,0xbf6dbf35,0x3f6d8000,0xbec43f35,0xbec4bf80,0x3f6d3f35,
0xbf6d8000,0x3ec4bf35,0x3ec43f80,0xbf6dbf35,0x3f6d8000,0xbec43f35,0xbec4bf80,0x3f6d3f35,0xbf7b0000,0x3f55bec4,0xbf0e3f35,0x3e48bf6d,
0xbe48bf80,0x3f0e3f6d,0xbf55bf35,0x3f7b3ec4,0x3f7b0000,0xbf553ec4,0x3f0ebf35,0xbe483f6d,0x3e483f80,0xbf0ebf6d,0x3f553f35,0xbf7bbec4,
0xbe48bf80,0x3f0e3f6d,0xbf55bf35,0x3f7b3ec4,0x3f7b8000,0xbf553ec4,0x3f0ebf35,0xbe483f6d,0x3e483f80,0xbf0ebf6d,0x3f553f35,0xbf7bbec4,
0xbf7b8000,0x3f55bec4,0xbf0e3f35,0x3e48bf6d,0xbf808000,0x3f808000,0xbf808000,0x3f808000,0xbf808000,0x3f808000,0xbf808000,0x3f808000,
0xbf808000,0x3f808000,0xbf808000,0x3f808000,0xbf808000,0x3f808000,0xbf808000,0x3f808000,0x3f80,0xbf80,0x3f80,0xbf80,
0x3f80,0xbf80,0x3f80,0xbf80,0x3f80,0xbf80,0x3f80,0xbf80,0x3f80,0xbf80,0x3f80,0xbf80,
0x3e48bf80,0xbf0e3f6d,0x3f55bf35,0xbf7b3ec4,0xbf7b8000,0x3f553ec4,0xbf0ebf35,0x3e483f6d,0xbe483f80,0x3f0ebf6d,0xbf553f35,0x3f7bbec4,
0x3f7b8000,0xbf55bec4,0x3f0e3f35,0xbe48bf6d,0xbf7b0000,0x3f553ec4,0xbf0ebf35,0x3e483f6d,0xbe483f80,0x3f0ebf6d,0xbf553f35,0x3f7bbec4,
0x3f7b0000,0xbf55bec4,0x3f0e3f35,0xbe48bf6d,0x3e48bf80,0xbf0e3f6d,0x3f55bf35,0xbf7b3ec4,0xbf6d8000,0x3ec43f35,0x3ec4bf80,0xbf6d3f35,
0x3f6d8000,0xbec4bf35,0xbec43f80,0x3f6dbf35,0xbf6d8000,0x3ec43f35,0x3ec4bf80,0xbf6d3f35,0x3f6d8000,0xbec4bf35,0xbec43f80,0x3f6dbf35,
0xbec43f80,0x3f6dbf35,0xbf6d0000,0x3ec43f35,0x3ec4bf80,0xbf6d3f35,0x3f6d0000,0xbec4bf35,0xbec43f80,0x3f6dbf35,0xbf6d0000,0x3ec43f35,
0x3ec4bf80,0xbf6d3f35,0x3f6d0000,0xbec4bf35,0x3f0ebf80,0xbf7b3ec4,0x3e483f35,0x3f55bf6d,0x3f558000,0x3e48bf6d,0xbf7b3f35,0x3f0e3ec4,
0xbf0e3f80,0x3f7bbec4,0xbe48bf35,0xbf553f6d,0xbf558000,0xbe483f6d,0x3f7bbf35,0xbf0ebec4,0xbf550000,0xbe483f6d,0x3f7bbf35,0xbf0ebec4,
0x3f0ebf80,0xbf7b3ec4,0x3e483f35,0x3f55bf6d,0x3f550000,0x3e48bf6d,0xbf7b3f35,0x3f0e3ec4,0xbf0e3f80,0x3f7bbec4,0xbe48bf35,0xbf553f6d,
0xbf353f80,0x3f350000,0x3f35bf80,0xbf350000,0xbf353f80,0x3f350000,0x3f35bf80,0xbf350000,0xbf353f80,0x3f350000,0x3f35bf80,0xbf350000,
0xbf353f80,0x3f350000,0x3f35bf80,0xbf350000,0xbf358000,0xbf353f80,0x3f358000,0x3f35bf80,0xbf358000,0xbf353f80,0x3f358000,0x3f35bf80,
0xbf358000,0xbf353f80,0x3f358000,0x3f35bf80,0xbf358000,0xbf353f80,0x3f358000,0x3f35bf80,0xbf0e0000,0xbf7b3f6d,0xbe483f35,0x3f55bec4,
0xbf553f80,0x3e483ec4,0x3f7bbf35,0x3f0ebf6d,0x3f0e0000,0x3f7bbf6d,0x3e48bf35,0xbf553ec4,0x3f55bf80,0xbe48bec4,0xbf7b3f35,0xbf0e3f6d,
0x3f55bf80,0xbe48bec4,0xbf7b3f35,0xbf0e3f6d,0xbf0e8000,0xbf7b3f6d,0xbe483f35,0x3f55bec4,0xbf553f80,0x3e483ec4,0x3f7bbf35,0x3f0ebf6d,
0x3f0e8000,0x3f7bbf6d,0x3e48bf35,0xbf553ec4,0xbf6d3f80,0xbec43f35,0x3ec40000,0x3f6dbf35,0x3f6dbf80,0x3ec4bf35,0xbec40000,0xbf6d3f35,
0xbf6d3f80,0xbec43f35,0x3ec40000,0x3f6dbf35,0x3f6dbf80,0x3ec4bf35,0xbec40000,0xbf6d3f35,0xbec48000,0xbf6d3f35,0xbf6d3f80,0xbec43f35,
0x3ec48000,0x3f6dbf35,0x3f6dbf80,0x3ec4bf35,0xbec48000,0xbf6d3f35,0xbf6d3f80,0xbec43f35,0x3ec48000,0x3f6dbf35,0x3f6dbf80,0x3ec4bf35,
0xbe480000,0xbf0e3ec4,0xbf553f35,0xbf7b3f6d,0x3f7bbf80,0x3f55bf6d,0x3f0ebf35,0x3e48bec4,0x3e480000,0x3f0ebec4,0x3f55bf35,0x3f7bbf6d,
0xbf7b3f80,0xbf553f6d,0xbf0e3f35,0xbe483ec4,0x3f7bbf80,0x3f55bf6d,0x3f0ebf35,0x3e48bec4,0x3e488000,0x3f0ebec4,0x3f55bf35,0x3f7bbf6d,
0xbf7b3f80,0xbf553f6d,0xbf0e3f35,0xbe483ec4,0xbe488000,0xbf0e3ec4,0xbf553f35,0xbf7b3f6d,0x80008000,0x80008000,0x80008000,0x80008000,
0x80008000,0x80008000,0x80008000,0x80008000,0x80008000,0x80008000,0x80008000,0x80008000,0x80008000,0x80008000,0x80008000,0x80008000,
0xbf803f80,0xbf803f80,0xbf803f80,0xbf803f80,0xbf803f80,0xbf803f80,0xbf803f80,0xbf803f80,0xbf803f80,0xbf803f80,0xbf803f80,0xbf803f80,
0xbf803f80,0xbf803f80,0xbf803f80,0xbf803f80,0x3f7bbf80,0x3f55bf6d,0x3f0ebf35,0x3e48bec4,0x3e488000,0x3f0ebec4,0x3f55bf35,0x3f7bbf6d,
0xbf7b3f80,0xbf553f6d,0xbf0e3f35,0xbe483ec4,0xbe488000,0xbf0e3ec4,0xbf553f35,0xbf7b3f6d,0x3e480000,0x3f0ebec4,0x3f55bf35,0x3f7bbf6d,
0xbf7b3f80,0xbf553f6d,0xbf0e3f35,0xbe483ec4,0xbe480000,0xbf0e3ec4,0xbf553f35,0xbf7b3f6d,0x3f7bbf80,0x3f55bf6d,0x3f0ebf35,0x3e48bec4,
0x3ec48000,0x3f6dbf35,0x3f6dbf80,0x3ec4bf35,0xbec48000,0xbf6d3f35,0xbf6d3f80,0xbec43f35,0x3ec48000,0x3f6dbf35,0x3f6dbf80,0x3ec4bf35,
0xbec48000,0xbf6d3f35,0xbf6d3f80,0xbec43f35,0xbf6d3f80,0xbec43f35,0x3ec40000,0x3f6dbf35,0x3f6dbf80,0x3ec4bf35,0xbec40000,0xbf6d3f35,
0xbf6d3f80,0xbec43f35,0x3ec40000,0x3f6dbf35,0x3f6dbf80,0x3ec4bf35,0xbec40000,0xbf6d3f35,0x3f55bf80,0xbe48bec4,0xbf7b3f35,0xbf0e3f6d,
0xbf0e8000,0xbf7b3f6d,0xbe483f35,0x3f55bec4,0xbf553f80,0x3e483ec4,0x3f7bbf35,0x3f0ebf6d,0x3f0e8000,0x3f7bbf6d,0x3e48bf35,0xbf553ec4,
0x3f0e0000,0x3f7bbf6d,0x3e48bf35,0xbf553ec4,0x3f55bf80,0xbe48bec4,0xbf7b3f35,0xbf0e3f6d,0xbf0e0000,0xbf7b3f6d,0xbe483f35,0x3f55bec4,
0xbf553f80,0x3e483ec4,0x3f7bbf35,0x3f0ebf6d,0xbf353f80,0x3f350000,0x3f35bf80,0xbf350000,0xbf353f80,0x3f350000,0x3f35bf80,0xbf350000,
0xbf353f80,0x3f350000,0x3f35bf80,0xbf350000,0xbf353f80,0x3f350000,0x3f35bf80,0xbf350000,0x3f358000,0x3f35bf80,0xbf358000,0xbf353f80,
0x3f358000,0x3f35bf80,0xbf358000,0xbf353f80,0x3f358000,0x3f35bf80,0xbf358000,0xbf353f80,0x3f358000,0x3f35bf80,0xbf358000,0xbf353f80,
0x3f550000,0x3e48bf6d,0xbf7b3f35,0x3f0e3ec4,0xbf0e3f80,0x3f7bbec4,0xbe48bf35,0xbf553f6d,0xbf550000,0xbe483f6d,0x3f7bbf35,0xbf0ebec4,
0x3f0ebf80,0xbf7b3ec4,0x3e483f35,0x3f55bf6d,0x3f0ebf80,0xbf7b3ec4,0x3e483f35,0x3f55bf6d,0x3f558000,0x3e48bf6d,0xbf7b3f35,0x3f0e3ec4,
0xbf0e3f80,0x3f7bbec4,0xbe48bf35,0xbf553f6d,0xbf558000,0xbe483f6d,0x3f7bbf35,0xbf0ebec4,0xbec43f80,0x3f6dbf35,0xbf6d0000,0x3ec43f35,
0x3ec4bf80,0xbf6d3f35,0x3f6d0000,0xbec4bf35,0xbec43f80,0x3f6dbf35,0xbf6d0000,0x3ec43f35,0x3ec4bf80,0xbf6d3f35,0x3f6d0000,0xbec4bf35,
0x3f6d8000,0xbec4bf35,0xbec43f80,0x3f6dbf35,0xbf6d8000,0x3ec43f35,0x3ec4bf80,0xbf6d3f35,0x3f6d8000,0xbec4bf35,0xbec43f80,0x3f6dbf35,
0xbf6d8000,0x3ec43f35,0x3ec4bf80,0xbf6d3f35,0x3f7b0000,0xbf55bec4,0x3f0e3f35,0xbe48bf6d,0x3e48bf80,0xbf0e3f6d,0x3f55bf35,0xbf7b3ec4,
0xbf7b0000,0x3f553ec4,0xbf0ebf35,0x3e483f6d,0xbe483f80,0x3f0ebf6d,0xbf553f35,0x3f7bbec4,0x3e48bf80,0xbf0e3f6d,0x3f55bf35,0xbf7b3ec4,
0xbf7b8000,0x3f553ec4,0xbf0ebf35,0x3e483f6d,0xbe483f80,0x3f0ebf6d,0xbf553f35,0x3f7bbec4,0x3f7b8000,0xbf55bec4,0x3f0e3f35,0xbe48bf6d,
0x3f808000,0xbf808000,0x3f808000,0xbf808000,0x3f808000,0xbf808000,0x3f808000,0xbf808000,0x3f808000,0xbf808000,0x3f808000,0xbf808000,
0x3f808000,0xbf808000,0x3f808000,0xbf808000,0x3f80,0xbf80,0x3f80,0xbf80,0x3f80,0xbf80,0x3f80,0xbf80,
0x3f80,0xbf80,0x3f80,0xbf80,0x3f80,0xbf80,0x3f80,0xbf80,0xbe48bf80,0x3f0e3f6d,0xbf55bf35,0x3f7b3ec4,
0x3f7b8000,0xbf553ec4,0x3f0ebf35,0xbe483f6d,0x3e483f80,0xbf0ebf6d,0x3f553f35,0xbf7bbec4,0xbf7b8000,0x3f55bec4,0xbf0e3f35,0x3e48bf6d,
0x3f7b0000,0xbf553ec4,0x3f0ebf35,0xbe483f6d,0x3e483f80,0xbf0ebf6d,0x3f553f35,0xbf7bbec4,0xbf7b0000,0x3f55bec4,0xbf0e3f35,0x3e48bf6d,
0xbe48bf80,0x3f0e3f6d,0xbf55bf35,0x3f7b3ec4,0x3f6d8000,0xbec43f35,0xbec4bf80,0x3f6d3f35,0xbf6d8000,0x3ec4bf35,0x3ec43f80,0xbf6dbf35,
0x3f6d8000,0xbec43f35,0xbec4bf80,0x3f6d3f35,0xbf6d8000,0x3ec4bf35,0x3ec43f80,0xbf6dbf35,0x3ec43f80,0xbf6dbf35,0x3f6d0000,0xbec43f35,
0xbec4bf80,0x3f6d3f35,0xbf6d0000,0x3ec4bf35,0x3ec43f80,0xbf6dbf35,0x3f6d0000,0xbec43f35,0xbec4bf80,0x3f6d3f35,0xbf6d0000,0x3ec4bf35,
0xbf0ebf80,0x3f7b3ec4,0xbe483f35,0xbf55bf6d,0xbf558000,0xbe48bf6d,0x3f7b3f35,0xbf0e3ec4,0x3f0e3f80,0xbf7bbec4,0x3e48bf35,0x3f553f6d,
0x3f558000,0x3e483f6d,0xbf7bbf35,0x3f0ebec4,0x3f550000,0x3e483f6d,0xbf7bbf35,0x3f0ebec4,0xbf0ebf80,0x3f7b3ec4,0xbe483f35,0xbf55bf6d,
0xbf550000,0xbe48bf6d,0x3f7b3f35,0xbf0e3ec4,0x3f0e3f80,0xbf7bbec4,0x3e48bf35,0x3f553f6d,0x3f353f80,0xbf350000,0xbf35bf80,0x3f350000,
0x3f353f80,0xbf350000,0xbf35bf80,0x3f350000,0x3f353f80,0xbf350000,0xbf35bf80,0x3f350000,0x3f353f80,0xbf350000,0xbf35bf80,0x3f350000,
0x3f358000,0x3f353f80,0xbf358000,0xbf35bf80,0x3f358000,0x3f353f80,0xbf358000,0xbf35bf80,0x3f358000,0x3f353f80,0xbf358000,0xbf35bf80,
0x3f358000,0x3f353f80,0xbf358000,0xbf35bf80,0x3f0e0000,0x3f7b3f6d,0x3e483f35,0xbf55bec4,0x3f553f80,0xbe483ec4,0xbf7bbf35,0xbf0ebf6d,
0xbf0e0000,0xbf7bbf6d,0xbe48bf35,0x3f553ec4,0xbf55bf80,0x3e48bec4,0x3f7b3f35,0x3f0e3f6d,0xbf55bf80,0x3e48bec4,0x3f7b3f35,0x3f0e3f6d,
0x3f0e8000,0x3f7b3f6d,0x3e483f35,0xbf55bec4,0x3f553f80,0xbe483ec4,0xbf7bbf35,0xbf0ebf6d,0xbf0e8000,0xbf7bbf6d,0xbe48bf35,0x3f553ec4,
0x3f6d3f80,0x3ec43f35,0xbec40000,0xbf6dbf35,0xbf6dbf80,0xbec4bf35,0x3ec40000,0x3f6d3f35,0x3f6d3f80,0x3ec43f35,0xbec40000,0xbf6dbf35,
0xbf6dbf80,0xbec4bf35,0x3ec40000,0x3f6d3f35,0x3ec48000,0x3f6d3f35,0x3f6d3f80,0x3ec43f35,0xbec48000,0xbf6dbf35,0xbf6dbf80,0xbec4bf35,
0x3ec48000,0x3f6d3f35,0x3f6d3f80,0x3ec43f35,0xbec48000,0xbf6dbf35,0xbf6dbf80,0xbec4bf35,0x3e480000,0x3f0e3ec4,0x3f553f35,0x3f7b3f6d,
0xbf7bbf80,0xbf55bf6d,0xbf0ebf35,0xbe48bec4,0xbe480000,0xbf0ebec4,0xbf55bf35,0xbf7bbf6d,0x3f7b3f80,0x3f553f6d,0x3f0e3f35,0x3e483ec4,
0xbf7bbf80,0xbf55bf6d,0xbf0ebf35,0xbe48bec4,0xbe488000,0xbf0ebec4,0xbf55bf35,0xbf7bbf6d,0x3f7b3f80,0x3f553f6d,0x3f0e3f35,0x3e483ec4,
0x3e488000,0x3f0e3ec4,0x3f553f35,0x3f7b3f6d,0x80003c00,0x80003c00,0x80003c00,0x80003c00,0x80003c00,0x80003c00,0x80003c00,0x80003c00,
0x80003c00,0x80003c00,0x80003c00,0x80003c00,0x80003c00,0x80003c00,0x80003c00,0x80003c00,0x80003c00,0x9e483c00,0xaa483bfe,0xab113bfd,
0xa2483c00,0xa4b63c00,0xabd93bfc,0xac513bfb,0xa6483bff,0xa7da3bff,0xacb53bfa,0xad1a3bf9,0xa8b63bff,0xa97f3bfe,0xad7e3bf8,0xade23bf7,
0x80003c00,0xa2483c00,0xae463bf6,0xaf0e3bf4,0xa6483bff,0xa8b63bff,0xafd63bf1,0xb04e3bed,0xaa483bfe,0xabd93bfc,0xb0b23bea,0xb1153be6,
0xacb53bfa,0xad7e3bf8,0xb1793be2,0xb1db3bdd,0x80003c00,0xa4b63c00,0xb0b23bea,0xb1473be4,0xa8b63bff,0xab113bfd,0xb1db3bdd,0xb26f3bd6,
0xacb53bfa,0xade23bf7,0xb3033bce,0xb3963bc6,0xaf0e3bf4,0xb01d3bef,0xb4143bbc,0xb45d3bb2,0x80003c00,0xa6483bff,0xb23e3bd9,0xb3033bce,
0xaa483bfe,0xacb53bfa,0xb3c63bc3,0xb4443bb6,0xae463bf6,0xafd63bf1,0xb4a53ba8,0xb5053b99,0xb0b23bea,0xb1793be2,0xb5643b88,0xb5c23b77,
0x80003c00,0xa7da3bff,0xb3c63bc3,0xb45d3bb2,0xabd93bfc,0xade23bf7,0xb4d53ba0,0xb54c3b8c,0xafd63bf1,0xb0e43be8,0xb5c23b77,0xb6373b5f,
0xb1db3bdd,0xb2d23bd1,0xb6aa3b46,0xb71b3b2b,0x80003c00,0xa8b63bff,0xb4a53ba8,0xb5343b91,0xacb53bfa,0xaf0e3bf4,0xb5c23b77,0xb64e3b5a,
0xb0b23bea,0xb1db3bdd,0xb6d73b3b,0xb75e3b1a,0xb3033bce,0xb4143bbc,0xb7e33af6,0xb8323ad0,0x80003c00,0xa97f3bfe,0xb5643b88,0xb6083b69,
0xad7e3bf8,0xb01d3bef,0xb6aa3b46,0xb7483b20,0xb1793be2,0xb2d23bd1,0xb7e33af6,0xb83d3ac9,0xb4143bbc,0xb4bd3ba4,0xb8873a99,0xb8ce3a65,
0x80003c00,0x80003c00,0x80003c00,0x80003c00,0x80003c00,0x80003c00,0x80003c00,0x80003c00,0x80003c00,0x80003c00,0x80003c00,0x80003c00,
0x80003c00,0x80003c00,0x80003c00,0x80003c00,0xae463bf6,0xaeaa3bf5,0xb0b23bea,0xb0e43be8,0xaf0e3bf4,0xaf723bf2,0xb1153be6,0xb1473be4,
0xafd63bf1,0xb01d3bef,0xb1793be2,0xb1aa3be0,0xb04e3bed,0xb0803bec,0xb1db3bdd,0xb20d3bdb,0xb23e3bd9,0xb2a13bd4,0xb4a53ba8,0xb4d53ba0,
0xb3033bce,0xb3653bc9,0xb5053b99,0xb5343b91,0xb3c63bc3,0xb4143bbc,0xb5643b88,0xb5933b80,0xb4443bb6,0xb4753baf,0xb5c23b77,0xb5f13b6e,
0xb4a53ba8,0xb4ed3b9d,0xb6d73b3b,0xb71b3b2b,0xb5343b91,0xb57c3b84,0xb75e3b1a,0xb7a13b08,0xb5c23b77,0xb6083b69,0xb7e33af6,0xb8123ae3,
0xb64e3b5a,0xb6933b4b,0xb8323ad0,0xb8523abc,0xb61f3b64,0xb67c3b50,0xb8723aa7,0xb89b3a8a,0xb6d73b3b,0xb7323b25,0xb8c43a6d,0xb8ec3a4f,
0xb78b3b0e,0xb7e33af6,0xb9133a2f,0xb93a3a0f,0xb81d3add,0xb8483ac2,0xb95f39ed,0xb98439cb,0xb78b3b0e,0xb7f93af0,0xb95f39ed,0xb98d39c3,
0xb8323ad0,0xb8673aae,0xb9ba3996,0xb9e53969,0xb89b3a8a,0xb8ce3a65,0xba0f393a,0xba373909,0xb9003a3f,0xb9303a17,0xba5e38d8,0xba8338a6,
0xb8723aa7,0xb8b03a7c,0xba2f3913,0xba5e38d8,0xb8ec3a4f,0xb9273a1f,0xba8a389b,0xbab5385d,0xb95f39ed,0xb99639ba,0xbadd381d,0xbb0237b7,
0xb9cb3984,0xb9fe394d,0xbb253732,0xbb4636aa,0xb9133a2f,0xb95639f6,0xbadd381d,0xbb0837a1,0xb99639ba,0xb9d4397b,0xbb303705,0xbb553665,
0xba0f393a,0xba4738f6,0xbb7735c2,0xbb95351d,0xba7c38b0,0xbaae3867,0xbbaf3475,0xbbc63396,0x80003c00,0xaa483bfe,0xb61f3b64,0xb6d73b3b,
0xae463bf6,0xb0b23bea,0xb78b3b0e,0xb81d3add,0xb23e3bd9,0xb3c63bc3,0xb8723aa7,0xb8c43a6d,0xb4a53ba8,0xb5643b88,0xb9133a2f,0xb95f39ed,
0x80003c00,0xab113bfd,0xb6d73b3b,0xb7a13b08,0xaf0e3bf4,0xb1473be4,0xb8323ad0,0xb8913a92,0xb3033bce,0xb45d3bb2,0xb8ec3a4f,0xb9433a07,
0xb5343b91,0xb6083b69,0xb99639ba,0xb9e53969,0x80003c00,0xabd93bfc,0xb78b3b0e,0xb8323ad0,0xafd63bf1,0xb1db3bdd,0xb89b3a8a,0xb9003a3f,
0xb3c63bc3,0xb4d53ba0,0xb95f39ed,0xb9ba3996,0xb5c23b77,0xb6aa3b46,0xba0f393a,0xba5e38d8,0x80003c00,0xac513bfb,0xb81d3add,0xb8913a92,
0xb04e3bed,0xb26f3bd6,0xb9003a3f,0xb96939e5,0xb4443bb6,0xb54c3b8c,0xb9cb3984,0xba27391d,0xb64e3b5a,0xb7483b20,0xba7c38b0,0xbac9383d,
0x80003c00,0xacb53bfa,0xb8723aa7,0xb8ec3a4f,0xb0b23bea,0xb3033bce,0xb95f39ed,0xb9cb3984,0xb4a53ba8,0xb5c23b77,0xba2f3913,0xba8a389b,
0xb6d73b3b,0xb7e33af6,0xbadd381d,0xbb253732,0x80003c00,0xad1a3bf9,0xb8c43a6d,0xb9433a07,0xb1153be6,0xb3963bc6,0xb9ba3996,0xba27391d,
0xb5053b99,0xb6373b5f,0xba8a389b,0xbae33812,0xb75e3b1a,0xb83d3ac9,0xbb303705,0xbb7235da,0x80003c00,0xad7e3bf8,0xb9133a2f,0xb99639ba,
0xb1793be2,0xb4143bbc,0xba0f393a,0xba7c38b0,0xb5643b88,0xb6aa3b46,0xbadd381d,0xbb303705,0xb7e33af6,0xb8873a99,0xbb7735c2,0xbbaf3475,
0x80003c00,0xade23bf7,0xb95f39ed,0xb9e53969,0xb1db3bdd,0xb45d3bb2,0xba5e38d8,0xbac9383d,0xb5c23b77,0xb71b3b2b,0xbb253732,0xbb7235da,
0xb8323ad0,0xb8ce3a65,0xbbaf3475,0xbbdb320d,0xb9a839a8,0xb9ed395f,0xbb64361f,0xbb883564,0xba2f3913,0xba6d38c4,0xbba834a5,0xbbc333c6,
0xbaa73872,0xbadd381d,0xbbd9323e,0xbbea30b2,0xbb0e378b,0xbb3b36d7,0xbbf62e46,0xbbfe2a48,0xba2f3913,0xba7438ba,0xbbc333c6,0xbbdb320d,
0xbab5385d,0xbaf037f9,0xbbed304e,0xbbf92d1a,0xbb253732,0xbb553665,0xbbff2648,0xbbffa7da,0xbb803593,0xbba434bd,0xbbf8ad7e,0xbbecb080,
0xbaa73872,0xbae93807,0xbbf62e46,0xbbff28b6,0xbb253732,0xbb5a364e,0xbbffa648,0xbbf8ad7e,0xbb883564,0xbbaf3475,0xbbeab0b2,0xbbd4b2a1,
0xbbce3303,0xbbe63115,0xbbb6b444,0xbb91b534,0xbb0e378b,0xbb4b3693,0xbbfeaa48,0xbbf2af72,0xbb803593,0xbbab348d,0xbbddb1db,0xbbc0b3f7,
0xbbce3303,0xbbe830e4,0xbb99b505,0xbb69b608,0xbbf82d7e,0xbc0024b6,0xbb30b705,0xbaf0b7f9,0xbb64361f,0xbb993505,0xbbd9b23e,0xbbb6b444,
0xbbc333c6,0xbbe23179,0xbb88b564,0xbb50b67c,0xbbf62e46,0xbbff2648,0xbb0eb78b,0xbac2b848,0xbbfeaa48,0xbbf1afd6,0xba6db8c4,0xba0fb93a,
0xbba834a5,0xbbd132d2,0xbb88b564,0xbb4bb693,0xbbed304e,0xbbfd2b11,0xbb02b7b7,0xbaaeb867,0xbbffa648,0xbbf5aeaa,0xba4fb8ec,0xb9e5b969,
0xbbddb1db,0xbbb9b42c,0xb972b9dc,0xb8f6ba47,0xbbd9323e,0xbbf42f0e,0xbb0eb78b,0xbab5b85d,0xbbff2648,0xbbfcabd9,0xba4fb8ec,0xb9dcb972,
0xbbeab0b2,0xbbc9b365,0xb95fb9ed,0xb8d8ba5e,0xbb99b505,0xbb5ab64e,0xb848bac2,0xb75ebb1a,0xbbf62e46,0xbc001e48,0xba6db8c4,0xb9f6b956,
0xbbf8ad7e,0xbbe0b1aa,0xb972b9dc,0xb8e2ba56,0xbbb6b444,0xbb7bb5ab,0xb848bac2,0xb748bb20,0xbb30b705,0xbad6b828,0xb5f1bb6e,0xb48dbbab,
0x80003c00,0xae463bf6,0xb9a839a8,0xba2f3913,0xb23e3bd9,0xb4a53ba8,0xbaa73872,0xbb0e378b,0xb61f3b64,0xb78b3b0e,0xbb64361f,0xbba834a5,
0xb8723aa7,0xb9133a2f,0xbbd9323e,0xbbf62e46,0x80003c00,0xaeaa3bf5,0xb9ed395f,0xba7438ba,0xb2a13bd4,0xb4ed3b9d,0xbae93807,0xbb4b3693,
0xb67c3b50,0xb7f93af0,0xbb993505,0xbbd132d2,0xb8b03a7c,0xb95639f6,0xbbf42f0e,0xbc001e48,0x80003c00,0xaf0e3bf4,0xba2f3913,0xbab5385d,
0xb3033bce,0xb5343b91,0xbb253732,0xbb803593,0xb6d73b3b,0xb8323ad0,0xbbc333c6,0xbbed304e,0xb8ec3a4f,0xb99639ba,0xbbff2648,0xbbf8ad7e,
0x80003c00,0xaf723bf2,0xba6d38c4,0xbaf037f9,0xb3653bc9,0xb57c3b84,0xbb5a364e,0xbbab348d,0xb7323b25,0xb8673aae,0xbbe23179,0xbbfd2b11,
0xb9273a1f,0xb9d4397b,0xbbfcabd9,0xbbe0b1aa,0x80003c00,0xafd63bf1,0xbaa73872,0xbb253732,0xb3c63bc3,0xb5c23b77,0xbb883564,0xbbce3303,
0xb78b3b0e,0xb89b3a8a,0xbbf62e46,0xbbffa648,0xb95f39ed,0xba0f393a,0xbbeab0b2,0xbbb6b444,0x80003c00,0xb01d3bef,0xbadd381d,0xbb553665,
0xb4143bbc,0xb6083b69,0xbbaf3475,0xbbe830e4,0xb7e33af6,0xb8ce3a65,0xbbff2648,0xbbf5aeaa,0xb99639ba,0xba4738f6,0xbbc9b365,0xbb7bb5ab,
0x80003c00,0xb04e3bed,0xbb0e378b,0xbb803593,0xb4443bb6,0xb64e3b5a,0xbbce3303,0xbbf82d7e,0xb81d3add,0xb9003a3f,0xbbfeaa48,0xbbddb1db,
0xb9cb3984,0xba7c38b0,0xbb99b505,0xbb30b705,0x80003c00,0xb0803bec,0xbb3b36d7,0xbba434bd,0xb4753baf,0xb6933b4b,0xbbe63115,0xbc0024b6,
0xb8483ac2,0xb9303a17,0xbbf1afd6,0xbbb9b42c,0xb9fe394d,0xbaae3867,0xbb5ab64e,0xbad6b828,0xbc000000,0xbbf6ae46,0xb9a8b9a8,0xb913ba2f,
0xbbd9b23e,0xbba8b4a5,0xb872baa7,0xb78bbb0e,0xbb64b61f,0xbb0eb78b,0xb61fbb64,0xb4a5bba8,0xbaa7b872,0xba2fb913,0xb23ebbd9,0xae46bbf6,
0xbbf6ae46,0xbbd6b26f,0xb8c4ba6d,0xb812bae3,0xbba0b4d5,0xbb55b665,0xb6aabb46,0xb51dbb95,0xbaf6b7e3,0xba83b8a6,0xb303bbce,0xaf72bbf2,
0xb9feb94d,0xb969b9e5,0xa248bc00,0x2de2bbf7,0xbbd9b23e,0xbba0b4d5,0xb78bbb0e,0xb5f1bb6e,0xbb50b67c,0xbae9b807,0xb444bbb6,0xb115bbe6,
0xba6db8c4,0xb9dcb972,0xaa48bbfe,0x2bd9bbfc,0xb93aba0f,0xb887ba99,0x3179bbe2,0x3475bbaf,0xbba8b4a5,0xbb55b665,0xb564bb88,0xb334bbcb,
0xbae9b807,0xba65b8ce,0xaf0ebbf4,0x1e48bc00,0xb9cbb984,0xb91dba27,0x2fd6bbf1,0x3396bbc6,0xb85dbab5,0xb71bbb2b,0x3593bb80,0x3748bb20,
0xbb64b61f,0xbaf6b7e3,0xb23ebbd9,0xacb5bbfa,0xba6db8c4,0xb9cbb984,0x2a48bbfe,0x3179bbe2,0xb913ba2f,0xb848bac2,0x34a5bba8,0x367cbb50,
0xb6d7bb3b,0xb505bb99,0x381dbadd,0x38ecba4f,0xbb0eb78b,0xba83b8a6,0xaa48bbfe,0x2d1abbf9,0xb9dcb972,0xb91dba27,0x32a1bbd4,0x354cbb8c,
0xb848bac2,0xb6c1bb41,0x3732bb25,0x387cbaa0,0xb4d5bba0,0xb1aabbe0,0x394db9fe,0x3a07b943,0xbaa7b872,0xb9feb94d,0x2e46bbf6,0x3365bbc9,
0xb93aba0f,0xb85dbab5,0x35c2bb77,0x37b7bb02,0xb6d7bb3b,0xb4d5bba0,0x38c4ba6d,0x3996b9ba,0xb179bbe2,0xa8b6bbff,0x3a4fb8ec,0x3ae9b807,
0xba2fb913,0xb969b9e5,0x33c6bbc3,0x3608bb69,0xb887ba99,0xb71bbb2b,0x3807bae9,0x38f6ba47,0xb505bb99,0xb1aabbe0,0x39cbb984,0x3a83b8a6,
0xa8b6bbff,0x2eaabbf5,0x3b1ab75e,0x3b8cb54c,0x80003c00,0xb0b23bea,0xbb64361f,0xbbc333c6,0xb4a53ba8,0xb6d73b3b,0xbbf62e46,0xbbfeaa48,
0xb8723aa7,0xb95f39ed,0xbbd9b23e,0xbb88b564,0xba2f3913,0xbadd381d,0xbb0eb78b,0xba6db8c4,0x80003c00,0xb0e43be8,0xbb883564,0xbbdb320d,
0xb4d53ba0,0xb71b3b2b,0xbbff28b6,0xbbf2af72,0xb89b3a8a,0xb98d39c3,0xbbb6b444,0xbb4bb693,0xba5e38d8,0xbb0837a1,0xbab5b85d,0xb9f6b956,
0x80003c00,0xb1153be6,0xbba834a5,0xbbed304e,0xb5053b99,0xb75e3b1a,0xbbffa648,0xbbddb1db,0xb8c43a6d,0xb9ba3996,0xbb88b564,0xbb02b7b7,
0xba8a389b,0xbb303705,0xba4fb8ec,0xb972b9dc,0x80003c00,0xb1473be4,0xbbc333c6,0xbbf92d1a,0xb5343b91,0xb7a13b08,0xbbf8ad7e,0xbbc0b3f7,
0xb8ec3a4f,0xb9e53969,0xbb50b67c,0xbaaeb867,0xbab5385d,0xbb553665,0xb9dcb972,0xb8e2ba56,0x80003c00,0xb1793be2,0xbbd9323e,0xbbff2648,
0xb5643b88,0xb7e33af6,0xbbeab0b2,0xbb99b505,0xb9133a2f,0xba0f393a,0xbb0eb78b,0xba4fb8ec,0xbadd381d,0xbb7735c2,0xb95fb9ed,0xb848bac2,
0x80003c00,0xb1aa3be0,0xbbea30b2,0xbbffa7da,0xb5933b80,0xb8123ae3,0xbbd4b2a1,0xbb69b608,0xb93a3a0f,0xba373909,0xbac2b848,0xb9e5b969,
0xbb0237b7,0xbb95351d,0xb8d8ba5e,0xb748bb20,0x80003c00,0xb1db3bdd,0xbbf62e46,0xbbf8ad7e,0xb5c23b77,0xb8323ad0,0xbbb6b444,0xbb30b705,
0xb95f39ed,0xba5e38d8,0xba6db8c4,0xb972b9dc,0xbb253732,0xbbaf3475,0xb848bac2,0xb5f1bb6e,0x80003c00,0xb20d3bdb,0xbbfe2a48,0xbbecb080,
0xb5f13b6e,0xb8523abc,0xbb91b534,0xbaf0b7f9,0xb98439cb,0xba8338a6,0xba0fb93a,0xb8f6ba47,0xbb4636aa,0xbbc63396,0xb75ebb1a,0xb48dbbab,
0xb9a8b9a8,0xb8c4ba6d,0x361fbb64,0x381dbadd,0xb78bbb0e,0xb564bb88,0x3913ba2f,0x39edb95f,0xb23ebbd9,0xaa48bbfe,0x3aa7b872,0x3b3bb6d7,
0x2e46bbf6,0x33c6bbc3,0x3ba8b4a5,0x3beab0b2,0xb913ba2f,0xb812bae3,0x381dbadd,0x391dba27,0xb5f1bb6e,0xb334bbcb,0x39feb94d,0x3abcb852,
0xacb5bbfa,0x2d1abbf9,0x3b50b67c,0x3bb9b42c,0x3365bbc9,0x3608bb69,0x3bf4af0e,0x3bfe297f,0xb872baa7,0xb6aabb46,0x3913ba2f,0x39feb94d,
0xb444bbb6,0xaf0ebbf4,0x3ac2b848,0x3b5ab64e,0x2a48bbfe,0x32a1bbd4,0x3bc3b3c6,0x3bf8ad7e,0x35c2bb77,0x3807bae9,0x3bfa2cb5,0x3bc93365,
0xb78bbb0e,0xb51dbb95,0x39edb95f,0x3abcb852,0xb115bbe6,0x1e48bc00,0x3b5ab64e,0x3bc6b396,0x3179bbe2,0x354cbb8c,0x3bfaacb5,0x3bf72de2,
0x37b7bb02,0x38f6ba47,0x3bbc3414,0x3b4b3693,0xb61fbb64,0xb303bbce,0x3aa7b872,0x3b50b67c,0xaa48bbfe,0x2fd6bbf1,0x3bc3b3c6,0x3bfaacb5,
0x34a5bba8,0x3732bb25,0x3bf62e46,0x3bb63444,0x38c4ba6d,0x39cbb984,0x3b3b36d7,0x3a8a389b,0xb4a5bba8,0xaf72bbf2,0x3b3bb6d7,0x3bb9b42c,
0x2bd9bbfc,0x3396bbc6,0x3bf8ad7e,0x3bf72de2,0x367cbb50,0x387cbaa0,0x3bb63444,0x3b3636ee,0x3996b9ba,0x3a83b8a6,0x3a7c38b0,0x398d39c3,
0xb23ebbd9,0xa248bc00,0x3ba8b4a5,0x3bf4af0e,0x3179bbe2,0x3593bb80,0x3bfa2cb5,0x3bbc3414,0x381dbadd,0x394db9fe,0x3b3b36d7,0x3a7c38b0,
0x3a4fb8ec,0x3b1ab75e,0x398439cb,0x385d3ab5,0xae46bbf6,0x2de2bbf7,0x3beab0b2,0x3bfe297f,0x3475bbaf,0x3748bb20,0x3bc93365,0x3b4b3693,
0x38ecba4f,0x3a07b943,0x3a8a389b,0x398d39c3,0x3ae9b807,0x3b8cb54c,0x385d3ab5,0x36083b69,
};
__device__ __align__(1024) bf16 g_hT[2304 * 2048];
__device__ __align__(1024) bf16 g_U[128 * 2 * 8 * 1024];
__device__ __align__(16) uint2 g_gate[2048];
__device__ __align__(16) uint4 g_agg[8 * 1024];
__device__ unsigned g_cnt[8 * 32];
constexpr int CNT_U = 0, CNT_V = 1, CNT_H = 2  , CNT_DONE = 4, CNT_EPOCH = 5;
#define PROFK(i) do { } while (0)
#define PROFC(i) do { } while (0)
#define PROF(i) do { } while (0)

constexpr int STAGE_BYTES = 49152;
constexpr int OFF_W = 0;
constexpr int OFF_F = 36864;
constexpr int OFF_TW = 45056;
constexpr int OFF_HS = 49152;
constexpr int OFF_A2 = 32768, OFF_B2 = 114688;
constexpr int OFF_U = 4 * STAGE_BYTES;
constexpr int OFF_G = OFF_U + 32768;
constexpr int OFF_T = OFF_G + 1024;
constexpr int OFF_BAR = OFF_T + 1024;
constexpr int OFF_REL = OFF_BAR + 192;
constexpr int OFF_GS = OFF_BAR + 224;
constexpr int SMEM_BYTES = OFF_GS + 128;
constexpr int BAR_FULL = 0  , BAR_FULL2 = 4  , BAR_X = 9, BAR_W = 10, BAR_U = 11, BAR_S0 = 12, BAR_H1 = 13, BAR_V = 14,
              BAR_G1 = 15, BAR_C = 16, BAR_CD = 17, BAR_H = 18  , NBAR = 22;

#define DEVI __device__ __forceinline__
constexpr unsigned SPIN_LIMIT = 1u << 22;

DEVI uint32_t smem_u32(const void* p) { return (uint32_t)__cvta_generic_to_shared(p); }
DEVI uint64_t gtime() { uint64_t t; asm volatile("mov.u64 %0, %%globaltimer;" : "=l"(t)); return t; }
DEVI void mbar_init(uint32_t bar, uint32_t cnt) { asm volatile("mbarrier.init.shared::cta.b64 [%0], %1;" :: "r"(bar), "r"(cnt) : "memory"); }
DEVI void mbar_expect_tx(uint32_t bar, uint32_t bytes) { asm volatile("mbarrier.arrive.expect_tx.shared::cta.b64 _, [%0], %1;" :: "r"(bar), "r"(bytes) : "memory"); }
DEVI void mbar_arrive(uint32_t bar) { asm volatile("mbarrier.arrive.shared::cta.b64 _, [%0];" :: "r"(bar) : "memory"); }
DEVI void mbar_wait(uint32_t bar, uint32_t parity) {
    asm volatile("{\n.reg .pred p;\n.reg .u32 n;\nmov.u32 n, 0;\n"
                 "LW:\nmbarrier.try_wait.parity.shared::cta.b64 p, [%0], %1;\n@p bra LD;\n"
                 "add.u32 n, n, 1;\nsetp.lt.u32 p, n, %2;\n@p bra LW;\nLD:\n}"
                 :: "r"(bar), "r"(parity), "n"(1 << 17) : "memory");
}
DEVI bool elect() {
    uint32_t p;
    asm volatile("{\n.reg .pred P;\nelect.sync _|P, 0xffffffff;\nselp.u32 %0, 1, 0, P;\n}" : "=r"(p));
    return p;
}
DEVI void fence_barrier_init() { asm volatile("fence.mbarrier_init.release.cluster;" ::: "memory"); }
DEVI void fence_proxy_async_smem() { asm volatile("fence.proxy.async.shared::cta;" ::: "memory"); }
DEVI void helper_sync() { asm volatile("bar.sync 1, 128;" ::: "memory"); }

DEVI void wait_counter(const unsigned* p, unsigned target) {
    for (unsigned n = 0;; n++) {
        unsigned v;
        asm volatile("ld.acquire.gpu.global.u32 %0, [%1];" : "=r"(v) : "l"(p) : "memory");
        if ((int)(v - target) >= 0 || n > SPIN_LIMIT) break;
    }
}
DEVI void signal_counter(unsigned* p) {
    asm volatile("red.relaxed.gpu.global.add.u32 [%0], 1;" :: "l"(p) : "memory");
}

DEVI void tma_load_3d(uint32_t dst, const CUtensorMap* map, uint32_t bar, int c0, int c1, int c2) {
    asm volatile("cp.async.bulk.tensor.3d.shared::cluster.global.mbarrier::complete_tx::bytes [%0], [%1, {%3, %4, %5}], [%2];"
        :: "r"(dst), "l"(map), "r"(bar), "r"(c0), "r"(c1), "r"(c2) : "memory");
}
DEVI void tma_load_4d(uint32_t dst, const CUtensorMap* map, uint32_t bar, int c0, int c1, int c2, int c3) {
    asm volatile("cp.async.bulk.tensor.4d.shared::cluster.global.mbarrier::complete_tx::bytes [%0], [%1, {%3, %4, %5, %6}], [%2];"
        :: "r"(dst), "l"(map), "r"(bar), "r"(c0), "r"(c1), "r"(c2), "r"(c3) : "memory");
}
DEVI void tma_store_5d(const CUtensorMap* map, uint32_t src, int c0, int c4) {
    asm volatile("cp.async.bulk.tensor.5d.global.shared::cta.bulk_group [%0, {%2, %4, %4, %4, %3}], [%1];"
        :: "l"(map), "r"(src), "r"(c0), "r"(c4), "r"(0) : "memory");
}
DEVI void tma_store_4d(const CUtensorMap* map, uint32_t src, int c0, int c1, int c2, int c3) {
    asm volatile("cp.async.bulk.tensor.4d.global.shared::cta.bulk_group [%0, {%2, %3, %4, %5}], [%1];"
        :: "l"(map), "r"(src), "r"(c0), "r"(c1), "r"(c2), "r"(c3) : "memory");
}
DEVI void bulk_load(uint32_t dst, const void* src, uint32_t bytes, uint32_t bar) {
    asm volatile("cp.async.bulk.shared::cluster.global.mbarrier::complete_tx::bytes [%0], [%1], %2, [%3];"
        :: "r"(dst), "l"(src), "r"(bytes), "r"(bar) : "memory");
}
DEVI void bulk_prefetch_l2(const void* src, uint32_t bytes) {
    asm volatile("cp.async.bulk.prefetch.L2.global [%0], %1;" :: "l"(src), "r"(bytes) : "memory");
}
DEVI void tma_store_3d(const CUtensorMap* map, uint32_t src, int c0, int c1, int c2) {
    asm volatile("cp.async.bulk.tensor.3d.global.shared::cta.bulk_group [%0, {%2, %3, %4}], [%1];"
        :: "l"(map), "r"(src), "r"(c0), "r"(c1), "r"(c2) : "memory");
}
DEVI void bulk_store(void* dst, uint32_t src, uint32_t bytes) {
    asm volatile("cp.async.bulk.global.shared::cta.bulk_group [%0], [%1], %2;" :: "l"(dst), "r"(src), "r"(bytes) : "memory");
}
DEVI void bulk_commit() { asm volatile("cp.async.bulk.commit_group;" ::: "memory"); }
DEVI void bulk_wait0() { asm volatile("cp.async.bulk.wait_group 0;" ::: "memory"); }
DEVI void bulk_wait1() { asm volatile("cp.async.bulk.wait_group 1;" ::: "memory"); }

DEVI void wgmma_fence() { asm volatile("wgmma.fence.sync.aligned;" ::: "memory"); }
DEVI void wgmma_commit() { asm volatile("wgmma.commit_group.sync.aligned;" ::: "memory"); }
template<int N> DEVI void wgmma_wait() { asm volatile("wgmma.wait_group.sync.aligned %0;" :: "n"(N) : "memory"); }
template<int N> DEVI void wgmma_wait_all(float (&d)[N]) {
    wgmma_wait<0>();
#pragma unroll
    for (int i = 0; i < N; i++) asm volatile("" : "+f"(d[i]) :: "memory");
}
template<int R> DEVI void reg_alloc() { asm volatile("setmaxnreg.inc.sync.aligned.u32 %0;" :: "n"(R)); }
template<int R> DEVI void reg_dealloc() { asm volatile("setmaxnreg.dec.sync.aligned.u32 %0;" :: "n"(R)); }

DEVI uint64_t make_desc(uint32_t addr, uint32_t lbo, uint32_t sbo, uint32_t mode = 1) {
    return (uint64_t)(((addr & 0x3FFFF) >> 4) | ((lbo >> 4) << 16)) | ((uint64_t)((sbo >> 4) | (mode << 30)) << 32);
}

#define ACC8(a, o) "+f"(a[o+0]), "+f"(a[o+1]), "+f"(a[o+2]), "+f"(a[o+3]), "+f"(a[o+4]), "+f"(a[o+5]), "+f"(a[o+6]), "+f"(a[o+7])
#define ACC32(a, o) ACC8(a, o), ACC8(a, o+8), ACC8(a, o+16), ACC8(a, o+24)

DEVI void wgmma_n256(float (&d)[128], uint64_t da, uint64_t db, int scale_d) {
    asm volatile("{\n.reg .pred p;\nsetp.ne.b32 p, %130, 0;\n"
        "wgmma.mma_async.sync.aligned.m64n256k16.f32.bf16.bf16 "
        "{%0, %1, %2, %3, %4, %5, %6, %7, %8, %9, %10, %11, %12, %13, %14, %15, "
        "%16, %17, %18, %19, %20, %21, %22, %23, %24, %25, %26, %27, %28, %29, %30, %31, "
        "%32, %33, %34, %35, %36, %37, %38, %39, %40, %41, %42, %43, %44, %45, %46, %47, "
        "%48, %49, %50, %51, %52, %53, %54, %55, %56, %57, %58, %59, %60, %61, %62, %63, "
        "%64, %65, %66, %67, %68, %69, %70, %71, %72, %73, %74, %75, %76, %77, %78, %79, "
        "%80, %81, %82, %83, %84, %85, %86, %87, %88, %89, %90, %91, %92, %93, %94, %95, "
        "%96, %97, %98, %99, %100, %101, %102, %103, %104, %105, %106, %107, %108, %109, %110, %111, "
        "%112, %113, %114, %115, %116, %117, %118, %119, %120, %121, %122, %123, %124, %125, %126, %127}, "
        "%128, %129, p, 1, 1, 0, 0;\n}\n"
        : ACC32(d, 0), ACC32(d, 32), ACC32(d, 64), ACC32(d, 96)
        : "l"(da), "l"(db), "r"(scale_d));
}
template<int TB>
DEVI void wgmma_n128(float (&d)[64], uint64_t da, uint64_t db, int scale_d) {
    asm volatile("{\n.reg .pred p;\nsetp.ne.b32 p, %66, 0;\n"
        "wgmma.mma_async.sync.aligned.m64n128k16.f32.bf16.bf16 "
        "{%0, %1, %2, %3, %4, %5, %6, %7, %8, %9, %10, %11, %12, %13, %14, %15, "
        "%16, %17, %18, %19, %20, %21, %22, %23, %24, %25, %26, %27, %28, %29, %30, %31, "
        "%32, %33, %34, %35, %36, %37, %38, %39, %40, %41, %42, %43, %44, %45, %46, %47, "
        "%48, %49, %50, %51, %52, %53, %54, %55, %56, %57, %58, %59, %60, %61, %62, %63}, "
        "%64, %65, p, 1, 1, 1, %67;\n}\n"
        : ACC32(d, 0), ACC32(d, 32)
        : "l"(da), "l"(db), "r"(scale_d), "n"(TB));
}
template<int SCALE_D>
DEVI void wgmma_rs_n128(float (&d)[64], const uint4& a, uint64_t db) {
    asm volatile("{\n.reg .pred p;\nsetp.ne.b32 p, %69, 0;\n"
        "wgmma.mma_async.sync.aligned.m64n128k16.f32.bf16.bf16 "
        "{%0, %1, %2, %3, %4, %5, %6, %7, %8, %9, %10, %11, %12, %13, %14, %15, "
        "%16, %17, %18, %19, %20, %21, %22, %23, %24, %25, %26, %27, %28, %29, %30, %31, "
        "%32, %33, %34, %35, %36, %37, %38, %39, %40, %41, %42, %43, %44, %45, %46, %47, "
        "%48, %49, %50, %51, %52, %53, %54, %55, %56, %57, %58, %59, %60, %61, %62, %63}, "
        "{%64, %65, %66, %67}, %68, p, 1, 1, 1;\n}\n"
        : ACC32(d, 0), ACC32(d, 32)
        : "r"(a.x), "r"(a.y), "r"(a.z), "r"(a.w), "l"(db), "n"(SCALE_D));
}
DEVI void wgmma_n16(float (&d)[8], uint64_t da, uint64_t db) {
    asm volatile("{\n.reg .pred p;\nsetp.ne.b32 p, 0, 0;\n"
        "wgmma.mma_async.sync.aligned.m64n16k16.f32.bf16.bf16 "
        "{%0, %1, %2, %3, %4, %5, %6, %7}, %8, %9, p, 1, 1, 1, 0;\n}\n"
        : ACC8(d, 0)
        : "l"(da), "l"(db));
}
template<int SCALE_D>
DEVI void wgmma_rs_n64(float (&d)[32], const uint32_t (&a)[4], uint64_t db) {
    asm volatile("{\n.reg .pred p;\nsetp.ne.b32 p, %37, 0;\n"
        "wgmma.mma_async.sync.aligned.m64n64k16.f32.bf16.bf16 "
        "{%0, %1, %2, %3, %4, %5, %6, %7, %8, %9, %10, %11, %12, %13, %14, %15, "
        "%16, %17, %18, %19, %20, %21, %22, %23, %24, %25, %26, %27, %28, %29, %30, %31}, "
        "{%32, %33, %34, %35}, %36, p, 1, 1, 0;\n}\n"
        : ACC32(d, 0)
        : "r"(a[0]), "r"(a[1]), "r"(a[2]), "r"(a[3]), "l"(db), "n"(SCALE_D));
}
DEVI void ldsm_x4_t(uint32_t (&r)[4], uint32_t addr) {
    asm volatile("ldmatrix.sync.aligned.m8n8.x4.trans.shared.b16 {%0, %1, %2, %3}, [%4];"
        : "=r"(r[0]), "=r"(r[1]), "=r"(r[2]), "=r"(r[3]) : "r"(addr) : "memory");
}
DEVI void stsm_x4(uint32_t addr, uint32_t r0, uint32_t r1, uint32_t r2, uint32_t r3) {
    asm volatile("stmatrix.sync.aligned.m8n8.x4.shared.b16 [%0], {%1, %2, %3, %4};"
        :: "r"(addr), "r"(r0), "r"(r1), "r"(r2), "r"(r3) : "memory");
}
DEVI void stsm_x4_t(uint32_t addr, uint32_t r0, uint32_t r1, uint32_t r2, uint32_t r3) {
    asm volatile("stmatrix.sync.aligned.m8n8.x4.trans.shared.b16 [%0], {%1, %2, %3, %4};"
        :: "r"(addr), "r"(r0), "r"(r1), "r"(r2), "r"(r3) : "memory");
}
DEVI uint32_t movm(uint32_t a) { uint32_t d; asm volatile("movmatrix.sync.aligned.m8n8.trans.b16 %0, %1;" : "=r"(d) : "r"(a)); return d; }
DEVI uint32_t pack2(float lo, float hi) { uint32_t d; asm("cvt.rn.bf16x2.f32 %0, %1, %2;" : "=r"(d) : "f"(hi), "f"(lo)); return d; }
DEVI float bf_lo(uint32_t v) { return __uint_as_float(v << 16); }
DEVI float bf_hi(uint32_t v) { return __uint_as_float(v & 0xffff0000u); }
DEVI float bf_round(float v) { return __bfloat162float(__float2bfloat16_rn(v)); }
DEVI uint32_t bf_mul2(uint32_t a, uint32_t b) { uint32_t d; asm("mul.rn.bf16x2 %0, %1, %2;" : "=r"(d) : "r"(a), "r"(b)); return d; }
DEVI uint4 lds128u(uint32_t a) { uint4 v; asm volatile("ld.shared.v4.u32 {%0, %1, %2, %3}, [%4];" : "=r"(v.x), "=r"(v.y), "=r"(v.z), "=r"(v.w) : "r"(a) : "memory"); return v; }
DEVI void sts128u(uint32_t a, uint32_t x, uint32_t y, uint32_t z, uint32_t w) { asm volatile("st.shared.v4.u32 [%0], {%1, %2, %3, %4};" :: "r"(a), "r"(x), "r"(y), "r"(z), "r"(w) : "memory"); }
DEVI uint2 lds64u(uint32_t a) { uint2 v; asm volatile("ld.shared.v2.u32 {%0, %1}, [%2];" : "=r"(v.x), "=r"(v.y) : "r"(a) : "memory"); return v; }
DEVI uint32_t ldg32u(const void* p) { uint32_t v; asm volatile("ld.global.nc.u32 %0, [%1];" : "=r"(v) : "l"(p) : "memory"); return v; }
DEVI void sts64(uint32_t a, float x, float y) { asm volatile("st.shared.v2.f32 [%0], {%1, %2};" :: "r"(a), "f"(x), "f"(y) : "memory"); }
DEVI uint32_t lds16(uint32_t a) { uint32_t v; asm volatile("ld.shared.u16 %0, [%1];" : "=r"(v) : "r"(a) : "memory"); return v; }
DEVI void sts16(uint32_t a, float v) { asm volatile("st.shared.u16 [%0], %1;" :: "r"(a), "r"(pack2(v, v)) : "memory"); }

DEVI float2 cmul(float2 a, float2 b) { return make_float2(fmaf(a.x, b.x, -a.y * b.y), fmaf(a.x, b.y, a.y * b.x)); }
DEVI float2 cfma(float2 a, float2 b, float2 c) { return make_float2(fmaf(a.x, b.x, fmaf(-a.y, b.y, c.x)), fmaf(a.x, b.y, fmaf(a.y, b.x, c.y))); }
DEVI float2 cadd(float2 a, float2 b) { return make_float2(a.x + b.x, a.y + b.y); }
DEVI float2 csub(float2 a, float2 b) { return make_float2(a.x - b.x, a.y - b.y); }
DEVI void fft4(float2& a, float2& b, float2& c, float2& d) {
    const float2 s0 = cadd(a, c), s1 = csub(a, c), s2 = cadd(b, d), t = csub(b, d), s3 = make_float2(t.y, -t.x);
    a = cadd(s0, s2); b = cadd(s1, s3); c = csub(s0, s2); d = csub(s1, s3);
}
DEVI float2 h2f(uint32_t v) { return __half22float2(*(const __half2*)&v); }

struct Params {
    const bf16 *x, *lam_re, *lam_im, *log_dt, *dskip, *gate_w, *c_re, *c_im, *w_r, *w_i;
    int swapB;
};

DEVI void pace(uint32_t cnt_addr) {
    uint32_t v0, v;
    asm volatile("ld.volatile.shared.u32 %0, [%1];" : "=r"(v0) : "r"(cnt_addr) : "memory");
    const unsigned t0 = clock();
    do {
        __nanosleep(20);
        asm volatile("ld.volatile.shared.u32 %0, [%1];" : "=r"(v) : "r"(cnt_addr) : "memory");
    } while (v == v0 && clock() - t0 < 1300u);
}

DEVI void helper_radix8(uint32_t sb, uint32_t gtab, int w, int lane) {
    const uint64_t dg = make_desc(gtab, 128, 256, 0);
    const uint32_t st = sb + OFF_U + (lane >> 4) * 16384 + (lane & 7) * 128 + (((2 * w + ((lane >> 3) & 1)) ^ (lane & 7)) << 4);
#pragma unroll 1
    for (int hf = 0; hf < 2; hf++) {
        float acc[8][8];
        const uint64_t da = make_desc(sb + OFF_U + hf * 8192, 16, 16384);
        wgmma_fence();
#pragma unroll
        for (int i = 0; i < 8; i++) wgmma_n16(acc[i], da + 64 * i, dg);
        wgmma_commit();
        wgmma_wait<0>();
        helper_sync();
#pragma unroll
        for (int i = 0; i < 8; i++)
            stsm_x4_t((st ^ ((i & 3) << 4)) + hf * 8192 + i * 1024,
                      pack2(acc[i][0], acc[i][1]), pack2(acc[i][2], acc[i][3]), pack2(acc[i][4], acc[i][5]), pack2(acc[i][6], acc[i][7]));
    }
}
DEVI uint32_t swz(uint32_t a) { return a ^ ((a >> 3) & 0x70); }

DEVI void c_mm(float (&acc)[2][32], const uint32_t (&a)[2][4][4], uint64_t df) {
    wgmma_fence();
#pragma unroll
    for (int h = 0; h < 2; h++) {
        wgmma_rs_n64<0>(acc[h], a[h][0], df);
        wgmma_rs_n64<1>(acc[h], a[h][1], df + 2);
        wgmma_rs_n64<1>(acc[h], a[h][2], df + 4);
        wgmma_rs_n64<1>(acc[h], a[h][3], df + 6);
    }
    wgmma_commit();
    wgmma_wait<0>();
}

DEVI void phase_c(uint32_t sb, int mrow, int warp, int lane) {
    PROFC(0);
    const uint64_t df = make_desc(sb + OFF_F, 16, 1024);
    const uint32_t tw_addr = sb + OFF_TW + lane * 16;
    uint32_t a[2][4][4];
    float acc[2][32];
    const uint32_t xa = sb + OFF_U + ((lane >> 4) * 4 + ((lane & 7) >> 1)) * 1024 + warp * 128
                      + ((((lane & 1) * 4 + ((lane >> 3) & 1)) ^ warp ^ ((lane >> 1) & 3)) << 4);
#pragma unroll
    for (int h = 0; h < 2; h++)
#pragma unroll
        for (int s = 0; s < 4; s++) ldsm_x4_t(a[h][s], (xa ^ (h * 32)) + (s & 1) * 8192 + (s >> 1) * 16384);
#pragma unroll 1
    for (int rep = 0; rep < 2; rep++) {
        PROFC(1 + 4 * rep);
        if (rep == 0 && warp >= 4) asm volatile("bar.sync 2, 256;" ::: "memory");
        c_mm(acc, a, df);
        if (rep == 0 && warp < 4) asm volatile("bar.arrive 2, 256;" ::: "memory");
        PROFC(2 + 4 * rep);
#pragma unroll
        for (int h = 0; h < 2; h++)
#pragma unroll
            for (int hh = 0; hh < 2; hh++)
#pragma unroll
                for (int jp = 0; jp < 2; jp++) {
                    const uint4 w = lds128u(tw_addr + ((h * 2 + hh) * 2 + jp) * 512);
#pragma unroll
                    for (int jl = 0; jl < 2; jl++) {
                        const int o = 8 * jp + 4 * jl + 2 * hh;
                        const float2 v0 = cmul(make_float2(acc[h][o], acc[h][16 + o]), h2f(jl ? w.z : w.x));
                        const float2 v1 = cmul(make_float2(acc[h][o + 1], acc[h][17 + o]), h2f(jl ? w.w : w.y));
                        a[jp][h][2 * hh + jl] = movm(pack2(v0.x, v1.x));
                        a[jp][2 + h][2 * hh + jl] = movm(pack2(v0.y, v1.y));
                    }
                }
        PROFC(3 + 4 * rep);
        c_mm(acc, a, df);
        PROFC(4 + 4 * rep);
        if (rep == 0) {
            const uint32_t w0 = sb + OFF_W + warp * 1152 + lane * 16, w1 = sb + OFF_W + 9216 + mrow * 1152 + lane * 16;
#pragma unroll
            for (int h = 0; h < 2; h++)
#pragma unroll
                for (int j = 0; j < 4; j++) {
                    const uint4 w = lds128u(((j >> 1) ? w1 : w0) + h * 18432 + (j & 1) * 512);
#pragma unroll
                    for (int hh = 0; hh < 2; hh++) {
                        const int o = 4 * j + 2 * hh;
                        const uint32_t u0 = hh ? w.z : w.x, u1 = hh ? w.w : w.y;
                        const float2 r0 = cmul(make_float2(acc[h][o], acc[h][16 + o]), make_float2(bf_lo(u0), bf_hi(u0)));
                        const float2 r1 = cmul(make_float2(acc[h][o + 1], acc[h][17 + o]), make_float2(bf_lo(u1), bf_hi(u1)));
                        a[h][j >> 1][2 * (j & 1) + hh] = pack2(r0.y, r1.y);
                        a[h][2 + (j >> 1)][2 * (j & 1) + hh] = pack2(r0.x, r1.x);
                    }
                }
        }
    }
#pragma unroll
    for (int h = 0; h < 2; h++)
#pragma unroll
        for (int s = 0; s < 4; s++) {
            const float* v = &acc[h][8 * s];
            stsm_x4_t((xa ^ (h * 32)) + (s & 1) * 8192 + ((s >> 1) ^ 1) * 16384,
                      pack2(v[0], v[1]), pack2(v[2], v[3]), pack2(v[4], v[5]), pack2(v[6], v[7]));
        }
}

#define PFW0 4
#define PFC0 8
__global__ void __cluster_dims__(2, 1, 1) __launch_bounds__(384, 1)
fused_kernel(const __grid_constant__ CUtensorMap mapB, const __grid_constant__ CUtensorMap mapX,
             const __grid_constant__ CUtensorMap mapXs, const __grid_constant__ CUtensorMap mapU0,
             const __grid_constant__ CUtensorMap mapU2, const __grid_constant__ CUtensorMap mapWr,
             const __grid_constant__ CUtensorMap mapWi, const __grid_constant__ CUtensorMap mapH2,
             const __grid_constant__ CUtensorMap mapH, const __grid_constant__ CUtensorMap mapCre,
             const __grid_constant__ CUtensorMap mapCim, const __grid_constant__ CUtensorMap mapV,
             const __grid_constant__ CUtensorMap mapO, const __grid_constant__ Params P) {
    extern __shared__ __align__(1024) uint8_t sm[];
    const uint32_t sb = smem_u32(sm);
    const uint32_t bars = sb + OFF_BAR, prog = sb + OFF_REL + 20;
    const int b = blockIdx.x, tid = threadIdx.x, warp = __shfl_sync(0xffffffffu, tid >> 5, 0), lane = tid & 31;
    const bool main_cta = b < 128;
    if (b == 129) return;
    const int b2 = ((b & 6) + ((b >> 4) & 1)) * 16 + (b & 8) + (b >> 5) * 2 + (b & 1);

    const int cls = b == 128 ? 128 : (b & 31) ? (b & 31) + 64 * (b >> 5) : (b == 64 ? 32 : b == 32 ? 64 : b);
    auto g1_stage = [](int it) { return it < 12 ? it & 3 : it == 15 ? 1 : it - 11; };
    auto load_g1 = [&](int it, int sg) {
        const uint32_t full = bars + 8 * (BAR_FULL + sg), st = sb + sg * STAGE_BYTES;
        mbar_expect_tx(full, STAGE_BYTES);
        tma_load_4d(st, &mapB, full, it * 64, 0, 0, (b & 15) * 8);
        tma_load_4d(st + 16384, &mapX, full, it * 64, 0, 0, (b >> 4) * 128);
    };
    auto load_c = [&](int k, int s) {
        const uint32_t full = bars + 8 * (BAR_FULL2 + s);
        mbar_expect_tx(full, 32768);
        tma_load_3d(sb + OFF_B2 + s * 16384, &mapCre + (k >> 4), full, 0, k < 32 ? (b2 & 14) * 64 : (k & 15) * 64, k < 32 ? k & 15 : b2 & ~1);
    };
    auto load_h = [&](int k, int s) {
        tma_load_3d(sb + OFF_A2 + s * 16384, &mapH, bars + 8 * (BAR_FULL2 + s), 0, k * 64, (k < 32 ? (b2 >> 4) * 4 : 0) + (b & 1) * 2);
    };
    if (elect()) {
        asm volatile("prefetch.tensormap [%0];" :: "l"(&mapB + warp) : "memory");
        if (warp == 8) {
            PROF(0);
#pragma unroll
            for (int i = 0; i < NBAR; i++) mbar_init(bars + 8 * i, i < BAR_G1 ? 1 : i == BAR_G1 ? 2 : i == BAR_C ? 128 : 8);
            *(uint4*)(sm + OFF_REL) = make_uint4(0, 0, 0, 0);
            *(uint2*)(sm + OFF_REL + 16) = make_uint2(0, 0);
            fence_barrier_init();
            fence_proxy_async_smem();
            if (main_cta) {
#pragma unroll 1
                for (int it = 0; it < 4; it++) load_g1(it, it);
            }
            PROF(27);
        }
    }
    __syncthreads();
    auto load_epoch = [&]() {
        unsigned e;
        asm volatile("ld.volatile.global.u32 %0, [%1];" : "=r"(e) : "l"(&g_cnt[CNT_EPOCH * 32]));
        return e + 1;
    };
    const int g = lane >> 2, q = lane & 3;

    if (warp < 8) {
        reg_alloc<192>();
        if (tid == 0) PROF(28);
        const int wg = warp >> 2;
        unsigned epoch = 0;
        auto release = [&](int s) -> bool {
            if (warp & 3) return false;
            unsigned old = 0;
            if (elect()) asm volatile("atom.relaxed.cta.shared.inc.u32 %0, [%1], 1;" : "=r"(old) : "r"(sb + OFF_REL + 4 * s) : "memory");
            return __any_sync(0xffffffffu, old == 1);
        };
        uint32_t xr[2][16], dk[16];
        const int trow = 64 * (16 * (b & 1) + 2 * warp) + 32 * (g & 1) + 8 * (g >> 1) + (b2 >> 4);
        const int dcol = (b2 & 14) * 64 + 2 * q;
        if (main_cta) {
            float acc[128];
            const int tc = b >> 4;
            const int pp = (b & 15) * 64 + (tid >> 2);
            const bf16 lr_ = P.lam_re[pp], li_ = P.lam_im[pp], ld_ = P.log_dt[pp];
            const int gn = 16 * (b & 15) + 2 * warp + (lane >> 4);
            const uint32_t goff = 16384 + gn * 128 + ((((lane & 15) >> 1) ^ (gn & 7)) << 4) + (lane & 1) * 8;
            const uint2* gwp = (const uint2*)P.gate_w + (lane & 15);
            uint2 gw = __ldg(gwp);
            float gs = 0.f;
#pragma unroll 1
            for (int it = 0; it < 16; it++) {
                const int sg = g1_stage(it);
                mbar_wait(bars + 8 * (BAR_FULL + sg), it < 12 ? (it >> 2) & 1 : it < 15);
                if (tid == 0) PROFK(it);
                const uint32_t st = sb + sg * STAGE_BYTES;
                const uint64_t da = make_desc(st + wg * 8192, 16, 1024), db = make_desc(st + 16384, 16, 1024);
                uint2 xv = lds64u(st + goff);
                wgmma_fence();
#pragma unroll
                for (int j = 0; j < 4; j++) wgmma_n256(acc, da + 2 * j, db + 2 * j, (it | j) != 0);
                wgmma_commit();
                xv.x = bf_mul2(xv.x, gw.x); xv.y = bf_mul2(xv.y, gw.y);
                gs += (bf_lo(xv.x) + bf_hi(xv.x)) + (bf_lo(xv.y) + bf_hi(xv.y));
                gw = __ldg(gwp + ((it + 1) & 15) * 16);
                wgmma_wait<1>();
                if (it > 0 && it < 14 && release(g1_stage(it - 1)) && elect()) {
                    if (it == 9) mbar_arrive(bars + 8 * BAR_S0);
                    else load_g1(it < 9 ? it + 3 : it + 2, g1_stage(it - 1));
                    asm volatile("st.volatile.shared.u32 [%0], %1;" :: "r"(prog), "r"(it) : "memory");
                }
                if (warp == 1 && elect()) {
                    if ((unsigned)(it - PFW0) < 4) bulk_prefetch_l2(((it & 1) ? P.w_i : P.w_r) + (size_t)(2 * b + (((it - PFW0) >> 1) & 1)) * 4104, 8208);
                    if ((unsigned)(it - PFC0) < 8) bulk_prefetch_l2(((b & 1) ? P.c_im : P.c_re) + (size_t)(b >> 1) * 16384 + (it - PFC0) * 2048, 4096);
                }
            }
            epoch = load_epoch();
            float2 lam1, lam8, lam64, lam128, wq, w4, l64q;
            float m00, m01, m10, m11, sg2;
            {
                const float lr = __bfloat162float(lr_), li = __bfloat162float(li_);
                const float dt = bf_round(expf(__bfloat162float(ld_)));
                const float mag = expf(dt * lr);
                float sn, cs; sincospif(dt * li * 0.31830988618379067f, &sn, &cs);
                lam1 = make_float2(mag * cs, mag * sn);
                const float inv = 1.f / (lr * lr + li * li);
                const float2 coef = cmul(make_float2(lam1.x - 1.f, lam1.y), make_float2(lr * inv, -li * inv));
                m00 = coef.x; m01 = -coef.y; m10 = -coef.y; m11 = -coef.x; sg2 = -1.f;
                if (P.swapB) { lam1.y = -lam1.y; m00 = -coef.y; m01 = coef.x; m10 = -coef.x; m11 = -coef.y; sg2 = 1.f; }
                float2 z = cmul(lam1, lam1);
                z = cmul(z, z); lam8 = cmul(z, z);
                z = cmul(lam8, lam8); z = cmul(z, z);
                lam64 = cmul(z, z); lam128 = cmul(lam64, lam64);
                const float2 l256 = cmul(lam128, lam128), l512 = cmul(l256, l256);
                w4 = cmul(l512, l512);
                const float2 one = make_float2(1.f, 0.f);
                wq = cmul((q & 1) ? l256 : one, (q & 2) ? l512 : one);
                l64q = cmul((q & 1) ? lam64 : one, (q & 2) ? lam128 : one);
            }
#pragma unroll
            for (int o = 1; o < 16; o <<= 1) gs += __shfl_xor_sync(0xffffffffu, gs, o);
            {
                const float gg = bf_round(__fdividef(1.f, 1.f + __expf(-bf_round(gs))));
                if ((lane & 15) == 0) *(uint2*)(sm + OFF_GS + (2 * warp + (lane >> 4)) * 8) = make_uint2(__float_as_uint(gg), __float_as_uint(2.f * bf_round(1.f - gg)));
            }
            wgmma_wait_all(acc);
            if ((tid & 127) == 0) mbar_arrive(bars + 8 * BAR_G1);
            if (tid == 0) PROF(3);
            float2 ag[8];
#pragma unroll
            for (int c = 0; c < 8; c++) ag[c] = make_float2(acc[16 * c], acc[16 * c + 2]);
#pragma unroll
            for (int r = 1; r < 8; r++)
#pragma unroll
                for (int c = 0; c < 8; c++) {
                    const int i = 16 * c + 4 * (r >> 1) + (r & 1);
                    ag[c] = cfma(lam1, ag[c], make_float2(acc[i], acc[i + 2]));
                }
            float2 v = ag[0];
#pragma unroll
            for (int c = 1; c < 8; c++) v = cfma(lam8, v, ag[c]);
            {
                float2 n = make_float2(__shfl_up_sync(0xffffffffu, v.x, 1, 4), __shfl_up_sync(0xffffffffu, v.y, 1, 4));
                if (q >= 1) v = cfma(lam64, n, v);
                n = make_float2(__shfl_up_sync(0xffffffffu, v.x, 2, 4), __shfl_up_sync(0xffffffffu, v.y, 2, 4));
                if (q >= 2) v = cfma(lam128, n, v);
            }
            if (q == 3 && tc < 7) {
                asm volatile("st.volatile.global.v4.u32 [%0], {%1, %2, %3, %4};"
                    :: "l"(&g_agg[tc * 1024 + pp]), "r"(__float_as_uint(v.x)), "r"(epoch), "r"(__float_as_uint(v.y)), "r"(epoch) : "memory");
            }
            float2 ex = make_float2(__shfl_up_sync(0xffffffffu, v.x, 1, 4), __shfl_up_sync(0xffffffffu, v.y, 1, 4));
            if (q == 0) ex = make_float2(0.f, 0.f);
            {
                uint32_t z;
                asm volatile("ld.volatile.shared.u32 %0, [%1];" : "=r"(z) : "r"(prog) : "memory");
                z >>= 16;
                m00 = __uint_as_float(__float_as_uint(m00) | z); m01 = __uint_as_float(__float_as_uint(m01) | z);
                m10 = __uint_as_float(__float_as_uint(m10) | z); m11 = __uint_as_float(__float_as_uint(m11) | z);
            }
            auto scale = [&](float& x, float& y) { const float u = fmaf(m00, x, m01 * y); y = fmaf(m10, x, m11 * y); x = u; };
#pragma unroll
            for (int i = 0; i < 128; i += 4) { scale(acc[i], acc[i + 2]); scale(acc[i + 1], acc[i + 3]); }
#pragma unroll
            for (int c = 0; c < 7; c++) scale(ag[c].x, ag[c].y);
            {
                float2 part = make_float2(0.f, 0.f);
                const int c0 = tc - 1 - q, c1 = tc - 5 - q;
                if (c0 >= 0) {
                    uint4 r0, r1 = make_uint4(0, epoch, 0, epoch);
                    for (unsigned n = 0;; n++) {
                        asm volatile("ld.volatile.global.v4.u32 {%0, %1, %2, %3}, [%4];" : "=r"(r0.x), "=r"(r0.y), "=r"(r0.z), "=r"(r0.w) : "l"(&g_agg[c0 * 1024 + pp]) : "memory");
                        if (c1 >= 0) asm volatile("ld.volatile.global.v4.u32 {%0, %1, %2, %3}, [%4];" : "=r"(r1.x), "=r"(r1.y), "=r"(r1.z), "=r"(r1.w) : "l"(&g_agg[c1 * 1024 + pp]) : "memory");
                        if ((r0.y == epoch && r0.w == epoch && r1.y == epoch && r1.w == epoch) || n > SPIN_LIMIT) break;
                    }
                    part = cfma(w4, make_float2(__uint_as_float(r1.x), __uint_as_float(r1.z)), make_float2(__uint_as_float(r0.x), __uint_as_float(r0.z)));
                    part = cmul(wq, part);
                }
                __syncwarp();
                part.x += __shfl_xor_sync(0xffffffffu, part.x, 1); part.y += __shfl_xor_sync(0xffffffffu, part.y, 1);
                part.x += __shfl_xor_sync(0xffffffffu, part.x, 2); part.y += __shfl_xor_sync(0xffffffffu, part.y, 2);
                ex = cfma(l64q, part, ex);
            }
            if (tid == 0) PROF(4);
            scale(ex.x, ex.y);
            lam1.y *= sg2; lam8.y *= sg2;
#pragma unroll
            for (int c = 0; c < 8; c++) { const float2 n = cfma(lam8, ex, ag[c]); ag[c] = ex; ex = n; }
            mbar_wait(bars + 8 * BAR_G1, 0);
#pragma unroll
            for (int r = 0; r < 8; r++) {
#pragma unroll
                for (int c = 0; c < 8; c++) {
                    const int i = 16 * c + 4 * (r >> 1) + (r & 1);
                    ag[c] = cfma(lam1, ag[c], make_float2(acc[i], acc[i + 2]));
                }
                const uint32_t hs = sb + OFF_HS + tid * 16 + r * 4096;
                sts128u(hs, pack2(ag[0].x, ag[4].x), pack2(ag[1].x, ag[5].x), pack2(ag[2].x, ag[6].x), pack2(ag[3].x, ag[7].x));
                sts128u(hs + 32768, pack2(ag[0].y, ag[4].y), pack2(ag[1].y, ag[5].y), pack2(ag[2].y, ag[6].y), pack2(ag[3].y, ag[7].y));
                if (r & 1) {
                    fence_proxy_async_smem();
                    __syncwarp();
                    if (lane == 0) mbar_arrive(bars + 8 * (BAR_H + (r >> 1)));
                }
            }
            if (tid == 0) PROF(5);
#pragma unroll
            for (int j = 0; j < 16; j++) {
                xr[0][j] = ldg32u(P.x + (size_t)trow * 1024 + dcol + 8 * j);
                xr[1][j] = ldg32u(P.x + (size_t)trow * 1024 + dcol + 8 * j + 65536);
                dk[j] = ldg32u(P.dskip + dcol + 8 * j);
            }
        }
        mbar_wait(bars + 8 * BAR_C, 0);
        if (tid == 0) PROF(6);
        phase_c(sb, b == 0 ? (8 - warp) & 7 : 7 - warp, warp, lane);
        fence_proxy_async_smem();
        __syncwarp();
        if (lane == 0) mbar_arrive(bars + 8 * BAR_CD);
        if (tid == 0) PROF(7);
        PROFC(9);
        if (main_cta) {
            float acc[64], acc2[64];
#pragma unroll
            for (int j = 0; j < 16; j++) {
                const uint32_t d0 = bf_mul2(dk[j], 0x3f003f00u), p0 = bf_mul2(xr[0][j], d0), p1 = bf_mul2(xr[1][j], d0);
                acc[4 * j] = bf_lo(p0); acc[4 * j + 1] = bf_hi(p0); acc[4 * j + 2] = bf_lo(p1); acc[4 * j + 3] = bf_hi(p1);
            }
#pragma unroll
            for (int i = 0; i < 64; i++) asm volatile("" : "+f"(acc[i]));
            mbar_wait(bars + 8 * (BAR_FULL2 + 1), 0);
            if (tid == 0) PROF(16);
            const float2* gp = (const float2*)&g_gate[(trow & ~255) + ((trow & 62) << 2) + ((trow >> 5) & 6) + (trow & 1)];
            const float2 g0 = __ldcg(gp), g1 = __ldcg(gp + 2);
            int s = 1, sp = 0; uint32_t ph = 0;
#pragma unroll 1
            for (int k = 0; k < 32; k++) {
                mbar_wait(bars + 8 * (BAR_FULL2 + s), ph);
                if (tid == 0 && (k & 1) == 0) PROFK(16 + (k >> 1));
                const uint64_t da = make_desc(sb + OFF_A2 + s * 16384 + wg * 8192, 16, 1024), db = make_desc(sb + OFF_B2 + s * 16384, 16, 1024);
                wgmma_fence();
#pragma unroll
                for (int j = 0; j < 4; j++) wgmma_n128<0>(acc, da + 128 * j, db + 2 * j, 1);
                wgmma_commit();
                wgmma_wait<1>();
                if (k > 0 && release(sp) && elect()) {
                    if ((k & 15) == 12) mbar_wait(bars + 8 * (BAR_H1 + (k >> 4)), 0);
                    load_c(k + 4, sp);
                    load_h(k + 4, sp);
                }
                sp = s;
                if (s == 0) ph ^= 1;
                if (++s == 5) s = 0;
            }
#pragma unroll
            for (int k = 0; k < 4; k++) {
                const int s = (k + 3) % 5;
                mbar_wait(bars + 8 * (BAR_FULL2 + s), k == 3);
                const uint64_t da = make_desc(sb + OFF_A2 + s * 16384 + wg * 8192, 16, 1024), db = make_desc(sb + OFF_B2 + s * 16384, 8192, 1024);
                wgmma_fence();
#pragma unroll
                for (int j = 0; j < 4; j++) wgmma_n128<1>(acc2, da + 128 * j, db + 128 * j, (k | j) != 0);
            }
            wgmma_commit();
            wgmma_wait_all(acc);
            wgmma_wait_all(acc2);
            if (tid == 0) PROF(17);
            const uint32_t ob = sb + (wg ? OFF_U : 0) + (warp & 3) * 8192, rr = 2 * (g & 3) + (g >> 2);
            const uint32_t oa = ob + rr * 128 + (((q >> 1) ^ rr) << 4) + (q & 1) * 8;
#pragma unroll
            for (int c = 0; c < 4; c++) {
#pragma unroll
                for (int j = 0; j < 4; j++) {
                    const int i = 16 * c + 4 * j;
                    sts64((oa ^ (j << 5)) + c * 2048, fmaf(g0.y, acc[i], g0.x * acc2[i]), fmaf(g0.y, acc[i + 1], g0.x * acc2[i + 1]));
                    sts64((oa ^ (j << 5)) + c * 2048 + 1024, fmaf(g1.y, acc[i + 2], g1.x * acc2[i + 2]), fmaf(g1.y, acc[i + 3], g1.x * acc2[i + 3]));
                }
                fence_proxy_async_smem();
                __syncwarp();
                if (elect()) tma_store_5d(&mapO, ob + c * 2048, (b2 >> 4) * 1024 + (b2 & 14) * 64 + 32 * c, 16 * (b & 1) + 2 * warp);
            }
            if (elect()) {
                bulk_commit();
                asm volatile("cp.async.bulk.wait_group.read 0;" ::: "memory");
            }
            if (tid == 0) PROF(19);
        }
        if (tid == 0) {
            const unsigned old = atomicAdd(&g_cnt[CNT_DONE * 32], 1u);
            if (old == 128) { g_cnt[CNT_DONE * 32] = 0; g_cnt[CNT_EPOCH * 32] = load_epoch(); }
        }
    } else {
        reg_dealloc<120>();
        const int t = tid - 256, w = warp - 8;
        if (w == 0 && main_cta && elect()) {
            mbar_expect_tx(bars + 8 * BAR_X, 32768);
            tma_load_4d(sb + OFF_U, &mapXs, bars + 8 * BAR_X, (b & 15) * 64, 0, 0, b >> 4);
            tma_load_4d(sb + OFF_U + 16384, &mapXs, bars + 8 * BAR_X, (b & 15) * 64 + 32, 0, 0, b >> 4);
            asm volatile("prefetch.tensormap [%0];" :: "l"(&mapO) : "memory");
        }
        const unsigned epoch = load_epoch();
        const bool real_cls = (cls & 127) == 0;
        const bool special = t < 4;
        const float R = 0.70710678118654752f;
        uint4 fa[4];
#pragma unroll
        for (int i = 0; i < 4; i++) fa[i] = __ldg((const uint4*)c_tab + i * 128 + t);
        float2 w1, w2, w3;
        {
            const int kk = (t >> 3) & 7, r = t & 7;
            float sn, cs;
            sincospif((float)(((cls + 256 * kk) * r) & 2047) * (1.f / 1024.f), &sn, &cs);
            sn *= 1.f / 1024.f; cs *= 1.f / 1024.f;
            const uint32_t gf = sb + OFF_G + kk * 16 + r * 2, gi = sb + OFF_G + 512 + r * 16 + kk * 2;
            if (t < 64) {
                sts16(gf, cs); sts16(gf + 128, real_cls ? 0.f : sn); sts16(gf + 256, -sn); sts16(gf + 384, real_cls ? 0.f : cs);
                sts16(gi, cs); sts16(gi + 128, -sn); sts16(gi + 256, sn); sts16(gi + 384, cs);
            }
            const int m = 2 * t - (t & 3);
            float s2, c2;
            sincospif((float)((cls * m) & 255) * (1.f / 128.f), &sn, &cs);
            sincospif((float)((cls * (m + 4)) & 255) * (1.f / 128.f), &s2, &c2);
            *(uint32_t*)(sm + OFF_T + t * 4) = b ? pack2(cs, c2) : 0x3f003f00u;
            *(uint32_t*)(sm + OFF_T + 512 + t * 4) = b ? pack2(-sn, -s2) : (t & 1) ? 0xbf00bf00u : 0x3f003f00u;
            sincospif((float)(8 * w + g) * (1.f / 128.f), &sn, &cs);
            w1 = make_float2(cs, -sn); w2 = cmul(w1, w1); w3 = cmul(w1, w2);
        }
        if (main_cta) {
            const uint32_t ua = sb + OFF_U + (lane >> 4) * 8192 + (8 * w + (lane & 7)) * 64 + ((((lane >> 3) & 1) ^ ((lane >> 1) & 3)) << 4);
            mbar_wait(bars + 8 * BAR_X, 0);
            if (t == 0) PROF(8);
#pragma unroll 1
            for (int hf = 0; hf < 2; hf++) {
                float acc[64];
                const uint64_t db = make_desc(sb + OFF_U + hf * 16384, 4096, 512, 2);
                wgmma_fence();
                wgmma_rs_n128<0>(acc, fa[0], db); wgmma_rs_n128<1>(acc, fa[1], db + 64); wgmma_rs_n128<1>(acc, fa[2], db + 128); wgmma_rs_n128<1>(acc, fa[3], db + 192);
                wgmma_commit();
                wgmma_wait_all(acc);
                helper_sync();
#pragma unroll
                for (int jp = 0; jp < 2; jp++) {
                    float2 y[4][4];
#pragma unroll
                    for (int i = 0; i < 4; i++) {
                        const int o = 8 * jp + 4 * (i >> 1) + (i & 1);
#pragma unroll
                        for (int m = 0; m < 4; m++) y[i][m] = make_float2(acc[16 * m + o], acc[16 * m + o + 2]);
                    }
                    if (special) {
#pragma unroll
                        for (int i = 0; i < 4; i++) {
                            const float2 s0 = cadd(y[i][0], y[i][2]), s1 = csub(y[i][0], y[i][2]), s2 = cadd(y[i][1], y[i][3]), s3 = csub(y[i][1], y[i][3]);
                            const float b0 = y[i][0].y, b2 = y[i][2].y;
                            y[i][0] = make_float2(s0.x + s2.x, s0.x - s2.x);
                            y[i][1] = make_float2(s1.x, -s3.x);
                            y[i][2] = make_float2(fmaf(R, s3.y, b0), fmaf(-R, s2.y, -b2));
                            y[i][3] = make_float2(fmaf(-R, s3.y, b0), fmaf(-R, s2.y, b2));
                        }
                    } else {
#pragma unroll
                        for (int i = 0; i < 4; i++) {
                            y[i][1] = cmul(y[i][1], w1); y[i][2] = cmul(y[i][2], w2); y[i][3] = cmul(y[i][3], w3);
                            fft4(y[i][0], y[i][1], y[i][2], y[i][3]);
                        }
                    }
                    __syncwarp();
#pragma unroll
                    for (int c = 0; c < 4; c++)
                        stsm_x4((ua ^ (jp * 32)) + hf * 16384 + c * 2048, pack2(y[0][c].x, y[1][c].x), pack2(y[2][c].x, y[3][c].x),
                                pack2(y[0][c].y, y[1][c].y), pack2(y[2][c].y, y[3][c].y));
                }
                fence_proxy_async_smem();
                helper_sync();
                if (w == 0 && elect()) {
                    tma_store_4d(&mapU0, sb + OFF_U + hf * 16384, (b & 15) * 64 + hf * 32, 0, 0, b >> 4);
                    bulk_store(g_hT + (size_t)(2048 + 2 * b + hf) * 2048, sb + OFF_T + hf * 512, 512);
                    bulk_commit();
                }
            }
        }
        if (w == 0 && elect()) {
            PROF(21);
            if (main_cta) {
                bulk_wait0();
                signal_counter(&g_cnt[CNT_U * 32]);
            }
            PROF(9);
            mbar_expect_tx(bars + 8 * BAR_U, 32768);
            wait_counter(&g_cnt[CNT_U * 32], epoch * 128);
            PROF(11);
#pragma unroll 1
            for (int i = 0; i < 2; i++) {
                pace(prog);
                tma_load_4d(sb + OFF_U + i * 16384, &mapU2, bars + 8 * BAR_U, 0, 0, 0, b == 128 ? 1 : b == 0 ? 0 : 2 * b + i);
            }
        }
        if (w == 1 && elect()) {
            const uint32_t bw = bars + 8 * BAR_W;
            if (main_cta) mbar_wait(bars + 8 * BAR_S0, 0);
            mbar_expect_tx(bw, 49152);
#pragma unroll 1
            for (int i = 0; i < 4; i++)
                tma_load_3d(sb + OFF_W + (i >> 1) * 9216 + (i & 1) * 18432, &mapWr + (i & 1), bw, 0, (1026 * (i < 2 ? cls : (256 - cls) & 255)) >> 7, 0);
            bulk_load(sb + OFF_F, c_tab + 2048, 12288, bw);
            PROF(10);
        }
        __syncwarp();
        mbar_wait(bars + 8 * BAR_W, 0);
        if (t == 0) PROF(23);
#pragma unroll 1
        for (int rr = 0; rr < 4; rr++) {
            const int row = 2 * w + (rr >> 1), mrow = b == 0 ? (8 - row) & 7 : 7 - row, mir = rr & 1;
            const uint32_t dp = OFF_W + row * 1152, mp = OFF_W + 9216 + mrow * 1152;
            const uint32_t dbase = dp + ((1026 * cls) & 127), mbase = mp + ((1026 * (256 - cls)) & 127);
            const int sg = mir ? -1 : 1;
            const uint32_t a0 = (mir ? mbase + 1024 : dbase) + sg * (2 * g + 128 * q);
            uint32_t wv[2][2][4];
#pragma unroll
            for (int h = 0; h < 2; h++)
#pragma unroll
                for (int j = 0; j < 2; j++)
#pragma unroll
                    for (int i = 0; i < 4; i++) {
                        const uint32_t ad = sb + swz(a0 + sg * (32 * h + 16 * (i >> 1) + 512 * j + 64 * (i & 1)));
                        wv[h][j][i] = (lds16(ad) | (lds16(ad + 18432) << 16)) ^ (mir << 31);
                    }
            if (lane == 0) {
                const uint32_t a2 = sb + swz(mir ? dbase + 1024 : mbase);
                wv[0][0][0] = pack2(0.5f * (bf_lo(wv[0][0][0]) + bf_lo(lds16(a2))), 0.5f * (bf_hi(wv[0][0][0]) - sg * bf_lo(lds16(a2 + 18432))));
            }
            __syncwarp();
#pragma unroll
            for (int h = 0; h < 2; h++)
#pragma unroll
                for (int j = 0; j < 2; j++)
                    sts128u(sb + (mir ? mp : dp) + h * 18432 + j * 512 + lane * 16, wv[h][j][0], wv[h][j][1], wv[h][j][2], wv[h][j][3]);
        }
        if (t == 0) PROF(12);
        fence_proxy_async_smem();
#pragma unroll 1
        for (int dir = 0; dir < 2; dir++) {
            if (dir == 0) {
                helper_sync();
                mbar_wait(bars + 8 * BAR_U, 0);
            } else {
                if (w == 0 && main_cta && elect()) {
                    mbar_wait(bars + 8 * BAR_G1, 0);
#pragma unroll 1
                    for (int k = 0; k < 5; k++) load_c(k, k == 4 ? 0 : k + 1);
#pragma unroll 1
                    for (int i = 0; i < 8; i++) {
                        if (i < 4) mbar_wait(bars + 8 * (BAR_H + i), 0);
                        if (i == 0) bulk_store(g_gate + 16 * b, sb + OFF_GS, 128);
                        tma_store_3d(&mapH2, sb + OFF_HS + i * 8192, (b >> 4) * 32, (i >> 2) * 1024 + (b & 15) * 64, 2 * (i & 3));
                        if (i == 3) bulk_commit();
                    }
                    bulk_commit();
                    bulk_wait1();
                    signal_counter(&g_cnt[CNT_H * 32]);
                    PROF(26);
                    wait_counter(&g_cnt[CNT_H * 32], epoch * 128);
                    PROF(1);
#pragma unroll 1
                    for (int k = 0; k < 5; k++) {
                        if (k == 2) { bulk_wait0(); signal_counter(&g_cnt[(CNT_H + 1) * 32]); PROF(2); }
                        if (k == 4) mbar_wait(bars + 8 * BAR_CD, 0);
                        load_h(k, k == 4 ? 0 : k + 1);
                    }
                }
                __syncwarp();
                mbar_wait(bars + 8 * BAR_CD, 0);
            }
            helper_radix8(sb, sb + OFF_G + dir * 512, w, lane);
            if (dir == 0) {
                mbar_arrive(bars + 8 * BAR_C);
                if (t == 0) PROF(22);
            }
        }
        fence_proxy_async_smem();
        helper_sync();
        if (w == 0 && elect()) {
            PROF(24);
            tma_store_4d(&mapU2, sb + OFF_U, 0, 0, 0, b == 128 ? 1 : 2 * b);
            if (!real_cls) tma_store_4d(&mapU2, sb + OFF_U + 16384, 0, 0, 0, 2 * b + 1);
            bulk_commit();
            bulk_wait0();
            signal_counter(&g_cnt[CNT_V * 32]);
            PROF(13);
            if (main_cta) {
                wait_counter(&g_cnt[(CNT_H + 1) * 32], epoch * 128);
                mbar_arrive(bars + 8 * BAR_H1);
                wait_counter(&g_cnt[CNT_V * 32], epoch * 129);
                mbar_arrive(bars + 8 * BAR_V);
                PROF(14);
            }
        }
    }
}

typedef CUresult (*PFN_encodeTiled)(CUtensorMap*, CUtensorMapDataType, cuuint32_t, void*, const cuuint64_t*, const cuuint64_t*,
                                    const cuuint32_t*, const cuuint32_t*, CUtensorMapInterleave, CUtensorMapSwizzle,
                                    CUtensorMapL2promotion, CUtensorMapFloatOOBfill);

static CUtensorMap make_map(PFN_encodeTiled enc, const void* ptr, int rank, const cuuint64_t* dims, const cuuint64_t* strides, const cuuint32_t* box,
                            CUtensorMapSwizzle sw = CU_TENSOR_MAP_SWIZZLE_128B, CUtensorMapDataType dt = CU_TENSOR_MAP_DATA_TYPE_BFLOAT16) {
    CUtensorMap m;
    cuuint32_t es[5] = {1, 1, 1, 1, 1};
    enc(&m, dt, rank, (void*)ptr, dims, strides, box, es, CU_TENSOR_MAP_INTERLEAVE_NONE,
        sw, CU_TENSOR_MAP_L2_PROMOTION_L2_128B, CU_TENSOR_MAP_FLOAT_OOB_FILL_NONE);
    return m;
}

extern "C" void kernel_launch(void* const* d_in, const int* in_sizes, int n_in, void* d_out, int out_size) {
    const bf16* x = (const bf16*)d_in[0];
    const bf16* wr = (const bf16*)d_in[1];
    const bf16* wi = (const bf16*)d_in[2];
    const bf16* Bre = (const bf16*)d_in[6];
    const bf16* Bim = (const bf16*)d_in[7];
    const bf16* Cre = (const bf16*)d_in[8];
    const bf16* Cim = (const bf16*)d_in[9];

    void* fn = nullptr;
    cudaDriverEntryPointQueryResult st;
    cudaGetDriverEntryPoint("cuTensorMapEncodeTiled", &fn, cudaEnableDefault, &st);
    PFN_encodeTiled enc = (PFN_encodeTiled)fn;
    void *p_hT, *p_U;
    cudaGetSymbolAddress(&p_hT, g_hT);
    cudaGetSymbolAddress(&p_U, g_U);

    Params P;
    P.x = x; P.lam_re = (const bf16*)d_in[4]; P.lam_im = (const bf16*)d_in[5]; P.log_dt = (const bf16*)d_in[10];
    P.dskip = (const bf16*)d_in[11]; P.gate_w = (const bf16*)d_in[12]; P.c_re = Cre; P.c_im = Cim; P.w_r = wr; P.w_i = wi;
    P.swapB = Bim < Bre;

    CUtensorMap mB, mX, mH, mCre, mCim, mXs, mU0, mV, mU2, mWr, mWi, mH2, mO;
    {
        const bf16* lo = P.swapB ? Bim : Bre; const bf16* hi = P.swapB ? Bre : Bim;
        cuuint64_t d[4] = {1024, 8, 2, 128}, s[3] = {2048, (cuuint64_t)((const char*)hi - (const char*)lo), 16384};
        cuuint32_t bx[4] = {64, 8, 2, 8};
        mB = make_map(enc, lo, 4, d, s, bx);
    }
    {
        cuuint64_t d[4] = {1024, 2, 4, 928}, s[3] = {2048, 64 * 2048, 2 * 2048};
        cuuint32_t bx[4] = {64, 2, 4, 32};
        mX = make_map(enc, x, 4, d, s, bx);
    }
    {
        cuuint64_t d[3] = {64, 2304, 32}, s[2] = {4096, 128};
        cuuint32_t bx[3] = {64, 64, 2};
        mH = make_map(enc, p_hT, 3, d, s, bx);
    }
    {
        cuuint64_t d[3] = {64, 1024, 16}, s[2] = {2048, 128};
        cuuint32_t bx[3] = {64, 128, 1};
        mCre = make_map(enc, Cre, 3, d, s, bx);
        mCim = make_map(enc, Cim, 3, d, s, bx);
    }
    {
        cuuint64_t d[3] = {64, 256, 128}, s[2] = {16384, 128};
        cuuint32_t bx[3] = {64, 64, 2};
        mV = make_map(enc, p_U, 3, d, s, bx);
    }
    {
        cuuint64_t d[5] = {8192, 2, 2, 2, 32}, s[4] = {16 * 4096, 32 * 4096, 8 * 4096, 64 * 4096};
        cuuint32_t bx[5] = {32, 2, 2, 2, 2};
        mO = make_map(enc, d_out, 5, d, s, bx, CU_TENSOR_MAP_SWIZZLE_128B, CU_TENSOR_MAP_DATA_TYPE_FLOAT32);
    }
    {
        cuuint64_t d[4] = {1024, 64, 4, 8}, s[3] = {32 * 2048, 8 * 2048, 2048};
        cuuint32_t bx[4] = {32, 64, 4, 1};
        mXs = make_map(enc, x, 4, d, s, bx, CU_TENSOR_MAP_SWIZZLE_64B);
    }
    {
        cuuint64_t d[4] = {1024, 128, 2, 8}, s[3] = {32768, 16384, 2048};
        cuuint32_t bx[4] = {32, 128, 2, 1};
        mU0 = make_map(enc, p_U, 4, d, s, bx, CU_TENSOR_MAP_SWIZZLE_64B);
    }
    {
        cuuint64_t d[4] = {64, 8, 16, 256}, s[3] = {2048, 128, 16384};
        cuuint32_t bx[4] = {64, 8, 16, 1};
        mU2 = make_map(enc, p_U, 4, d, s, bx);
    }
    {
        cuuint64_t d[3] = {64, 2052, 8}, s[2] = {128, 262656};
        cuuint32_t bx[3] = {64, 9, 8};
        mWr = make_map(enc, wr, 3, d, s, bx);
        mWi = make_map(enc, wi, 3, d, s, bx);
    }
    {
        cuuint64_t d[3] = {256, 2048, 8}, s[2] = {4096, 512};
        cuuint32_t bx[3] = {32, 64, 2};
        mH2 = make_map(enc, p_hT, 3, d, s, bx, CU_TENSOR_MAP_SWIZZLE_NONE);
    }
    cudaFuncSetAttribute(fused_kernel, cudaFuncAttributeMaxDynamicSharedMemorySize, SMEM_BYTES);
    fused_kernel<<<130, 384, SMEM_BYTES, cudaStreamPerThread>>>(mB, mX, mXs, mU0, mU2, mWr, mWi, mH2, mH, mCre, mCim, mV, mO, P);
}
```

```cpp
#include <cuda_runtime.h>
#include <cuda_bf16.h>
#include <cuda.h>
#include <stdint.h>

typedef __nv_bfloat16 bf16;

__device__ const __align__(128) uint32_t c_tab[5120] = {
0x3f803f80,0xbf803f80,0x3f803f80,0xbf803f80,0x3f803f80,0xbf803f80,0x3f803f80,0xbf803f80,0x3f803f80,0xbf803f80,0x3f803f80,0xbf803f80,
0x3f803f80,0xbf803f80,0x3f803f80,0xbf803f80,0x3f7f3f80,0xbdc98000,0x3f223f35,0xbf46bf35,0x3f753f7b,0xbe95be48,0x3ef13f0e,0xbf62bf55,
0x3f623f6d,0xbef1bec4,0x3e953ec4,0xbf75bf6d,0x3f463f55,0xbf22bf0e,0x3dc93e48,0xbf7fbf7b,0x3f7b3f80,0xbe488000,0xbe480000,0xbf7bbf80,
0x3f553f6d,0xbf0ebec4,0xbf0ebec4,0xbf55bf6d,0x3f0e3f35,0xbf55bf35,0xbf55bf35,0xbf0ebf35,0x3e483ec4,0xbf7bbf6d,0xbf7bbf6d,0xbe48bec4,
0x3f753f80,0xbe958000,0xbf62bf35,0xbef1bf35,0x3f223f55,0xbf46bf0e,0xbf7fbf7b,0x3dc9be48,0x3dc93ec4,0xbf7fbf6d,0xbf46bf6d,0x3f223ec4,
0xbef1be48,0xbf62bf7b,0xbe95bf0e,0x3f753f55,0x3f6d3f80,0xbec48000,0xbf6dbf80,0x3ec48000,0x3ec43f35,0xbf6dbf35,0xbec4bf35,0x3f6d3f35,
0xbec40000,0xbf6dbf80,0x3ec40000,0x3f6d3f80,0xbf6dbf35,0xbec4bf35,0x3f6d3f35,0x3ec43f35,0x3f623f80,0xbef18000,0xbe95bf35,0x3f753f35,
0x3dc93f0e,0xbf7fbf55,0x3f223e48,0x3f463f7b,0xbf46bec4,0xbf22bf6d,0x3f7f3f6d,0xbdc93ec4,0xbf75bf7b,0x3e95be48,0x3ef13f55,0xbf62bf0e,
0x3f553f80,0xbf0e8000,0x3f0e0000,0x3f553f80,0xbe483ec4,0xbf7bbf6d,0x3f7b3f6d,0xbe483ec4,0xbf7bbf35,0xbe48bf35,0x3e483f35,0xbf7bbf35,
0xbf0ebf6d,0x3f553ec4,0xbf55bec4,0xbf0ebf6d,0x3f463f80,0xbf228000,0x3f7f3f35,0x3dc93f35,0xbef13e48,0xbf62bf7b,0x3e953f55,0xbf75bf0e,
0xbf75bf6d,0x3e95bec4,0xbf62bec4,0xbef1bf6d,0x3dc9bf0e,0x3f7f3f55,0xbf22bf7b,0x3f463e48,0x3f353f80,0xbf358000,0x3f353f80,0xbf358000,
0xbf350000,0xbf35bf80,0xbf350000,0xbf35bf80,0xbf35bf80,0x3f358000,0xbf35bf80,0x3f358000,0x3f350000,0x3f353f80,0x3f350000,0x3f353f80,
0x3f223f80,0xbf468000,0xbdc93f35,0xbf7fbf35,0xbf62be48,0xbef1bf7b,0xbf75bf55,0x3e95bf0e,0xbe95bf6d,0x3f753ec4,0x3ef1bec4,0x3f623f6d,
0x3f7f3f0e,0x3dc93f55,0x3f463f7b,0xbf223e48,0x3f0e3f80,0xbf558000,0xbf550000,0xbf0ebf80,0xbf7bbec4,0xbe48bf6d,0xbe48bf6d,0x3f7b3ec4,
0x3e48bf35,0x3f7b3f35,0x3f7b3f35,0xbe483f35,0x3f553f6d,0xbf0e3ec4,0xbf0e3ec4,0xbf55bf6d,0x3ef13f80,0xbf628000,0xbf75bf35,0x3e95bf35,
0xbf7fbf0e,0x3dc9bf55,0x3f46be48,0x3f223f7b,0x3f22bec4,0x3f463f6d,0x3dc93f6d,0xbf7fbec4,0x3e953f7b,0xbf75be48,0xbf62bf55,0x3ef1bf0e,
0x3ec43f80,0xbf6d8000,0xbec4bf80,0x3f6d8000,0xbf6dbf35,0x3ec4bf35,0x3f6d3f35,0xbec43f35,0x3f6d0000,0x3ec43f80,0xbf6d0000,0xbec4bf80,
0xbec43f35,0xbf6dbf35,0x3ec4bf35,0x3f6d3f35,0x3e953f80,0xbf758000,0x3ef1bf35,0x3f623f35,0xbf46bf55,0x3f22bf0e,0x3dc93f7b,0xbf7fbe48,
0x3f7f3ec4,0xbdc93f6d,0xbf22bf6d,0x3f46bec4,0xbf623e48,0xbef1bf7b,0x3f753f0e,0xbe953f55,0x3e483f80,0xbf7b8000,0x3f7b0000,0x3e483f80,
0xbf0ebf6d,0x3f55bec4,0xbf553ec4,0xbf0ebf6d,0x3f553f35,0xbf0e3f35,0x3f0ebf35,0x3f553f35,0xbf7bbec4,0x3e48bf6d,0xbe483f6d,0xbf7bbec4,
0x3dc93f80,0xbf7f8000,0x3f463f35,0xbf223f35,0xbe95bf7b,0x3f75be48,0xbf62bf0e,0x3ef1bf55,0x3ef13f6d,0xbf623ec4,0x3f753ec4,0xbe953f6d,
0xbf22bf55,0x3f46bf0e,0xbf7fbe48,0x3dc9bf7b,0x3f80,0xbf808000,0x3f80,0xbf808000,0xbf80,0x3f808000,0xbf80,0x3f808000,
0x3f80,0xbf808000,0x3f80,0xbf808000,0xbf80,0x3f808000,0xbf80,0x3f808000,0xbdc93f80,0xbf7f8000,0xbf463f35,0xbf22bf35,
0x3e95bf7b,0x3f753e48,0x3f62bf0e,0x3ef13f55,0xbef13f6d,0xbf62bec4,0xbf753ec4,0xbe95bf6d,0x3f22bf55,0x3f463f0e,0x3f7fbe48,0x3dc93f7b,
0xbe483f80,0xbf7b8000,0xbf7b0000,0x3e48bf80,0x3f0ebf6d,0x3f553ec4,0x3f553ec4,0xbf0e3f6d,0xbf553f35,0xbf0ebf35,0xbf0ebf35,0x3f55bf35,
0x3f7bbec4,0x3e483f6d,0x3e483f6d,0xbf7b3ec4,0xbe953f80,0xbf758000,0xbef1bf35,0x3f62bf35,0x3f46bf55,0x3f223f0e,0xbdc93f7b,0xbf7f3e48,
0xbf7f3ec4,0xbdc9bf6d,0x3f22bf6d,0x3f463ec4,0x3f623e48,0xbef13f7b,0xbf753f0e,0xbe95bf55,0xbec43f80,0xbf6d8000,0x3ec4bf80,0x3f6d8000,
0x3f6dbf35,0x3ec43f35,0xbf6d3f35,0xbec4bf35,0xbf6d0000,0x3ec4bf80,0x3f6d0000,0xbec43f80,0x3ec43f35,0xbf6d3f35,0xbec4bf35,0x3f6dbf35,
0xbef13f80,0xbf628000,0x3f75bf35,0x3e953f35,0x3f7fbf0e,0x3dc93f55,0xbf46be48,0x3f22bf7b,0xbf22bec4,0x3f46bf6d,0xbdc93f6d,0xbf7f3ec4,
0xbe953f7b,0xbf753e48,0x3f62bf55,0x3ef13f0e,0xbf0e3f80,0xbf558000,0x3f550000,0xbf0e3f80,0x3f7bbec4,0xbe483f6d,0x3e48bf6d,0x3f7bbec4,
0xbe48bf35,0x3f7bbf35,0xbf7b3f35,0xbe48bf35,0xbf553f6d,0xbf0ebec4,0x3f0e3ec4,0xbf553f6d,0xbf223f80,0xbf468000,0x3dc93f35,0xbf7f3f35,
0x3f62be48,0xbef13f7b,0x3f75bf55,0x3e953f0e,0x3e95bf6d,0x3f75bec4,0xbef1bec4,0x3f62bf6d,0xbf7f3f0e,0x3dc9bf55,0xbf463f7b,0xbf22be48,
0xbf353f80,0xbf358000,0xbf353f80,0xbf358000,0x3f350000,0xbf353f80,0x3f350000,0xbf353f80,0x3f35bf80,0x3f358000,0x3f35bf80,0x3f358000,
0xbf350000,0x3f35bf80,0xbf350000,0x3f35bf80,0xbf463f80,0xbf228000,0xbf7f3f35,0x3dc9bf35,0x3ef13e48,0xbf623f7b,0xbe953f55,0xbf753f0e,
0x3f75bf6d,0x3e953ec4,0x3f62bec4,0xbef13f6d,0xbdc9bf0e,0x3f7fbf55,0x3f22bf7b,0x3f46be48,0xbf553f80,0xbf0e8000,0xbf0e0000,0x3f55bf80,
0x3e483ec4,0xbf7b3f6d,0xbf7b3f6d,0xbe48bec4,0x3f7bbf35,0xbe483f35,0xbe483f35,0xbf7b3f35,0x3f0ebf6d,0x3f55bec4,0x3f55bec4,0xbf0e3f6d,
0xbf623f80,0xbef18000,0x3e95bf35,0x3f75bf35,0xbdc93f0e,0xbf7f3f55,0xbf223e48,0x3f46bf7b,0x3f46bec4,0xbf223f6d,0xbf7f3f6d,0xbdc9bec4,
0x3f75bf7b,0x3e953e48,0xbef13f55,0xbf623f0e,0xbf6d3f80,0xbec48000,0x3f6dbf80,0x3ec48000,0xbec43f35,0xbf6d3f35,0x3ec4bf35,0x3f6dbf35,
0x3ec40000,0xbf6d3f80,0xbec40000,0x3f6dbf80,0x3f6dbf35,0xbec43f35,0xbf6d3f35,0x3ec4bf35,0xbf753f80,0xbe958000,0x3f62bf35,0xbef13f35,
0xbf223f55,0xbf463f0e,0x3f7fbf7b,0x3dc93e48,0xbdc93ec4,0xbf7f3f6d,0x3f46bf6d,0x3f22bec4,0x3ef1be48,0xbf623f7b,0x3e95bf0e,0x3f75bf55,
0xbf7b3f80,0xbe488000,0x3e480000,0xbf7b3f80,0xbf553f6d,0xbf0e3ec4,0x3f0ebec4,0xbf553f6d,0xbf0e3f35,0xbf553f35,0x3f55bf35,0xbf0e3f35,
0xbe483ec4,0xbf7b3f6d,0x3f7bbf6d,0xbe483ec4,0xbf7f3f80,0xbdc98000,0xbf223f35,0xbf463f35,0xbf753f7b,0xbe953e48,0xbef13f0e,0xbf623f55,
0xbf623f6d,0xbef13ec4,0xbe953ec4,0xbf753f6d,0xbf463f55,0xbf223f0e,0xbdc93e48,0xbf7f3f7b,0x3f803f80,0xbf803f80,0x3f803f80,0xbf803f80,
0x3f803f80,0xbf803f80,0x3f803f80,0xbf803f80,0x3f803f80,0xbf803f80,0x3f803f80,0xbf803f80,0x3f803f80,0xbf803f80,0x3f803f80,0xbf803f80,
0xbdc90000,0xbf7fbf80,0xbf46bf35,0xbf22bf35,0xbe95be48,0xbf75bf7b,0xbf62bf55,0xbef1bf0e,0xbef1bec4,0xbf62bf6d,0xbf75bf6d,0xbe95bec4,
0xbf22bf0e,0xbf46bf55,0xbf7fbf7b,0xbdc9be48,0xbf7bbf80,0x3e488000,0x3e480000,0x3f7b3f80,0xbf55bf6d,0x3f0e3ec4,0x3f0e3ec4,0x3f553f6d,
0xbf0ebf35,0x3f553f35,0x3f553f35,0x3f0e3f35,0xbe48bec4,0x3f7b3f6d,0x3f7b3f6d,0x3e483ec4,0x3e950000,0x3f753f80,0x3ef13f35,0xbf62bf35,
0x3f463f0e,0x3f223f55,0xbdc93e48,0xbf7fbf7b,0x3f7f3f6d,0x3dc93ec4,0xbf22bec4,0xbf46bf6d,0x3f623f7b,0xbef1be48,0xbf75bf55,0xbe95bf0e,
0x3f6d3f80,0xbec48000,0xbf6dbf80,0x3ec48000,0x3ec43f35,0xbf6dbf35,0xbec4bf35,0x3f6d3f35,0xbec40000,0xbf6dbf80,0x3ec40000,0x3f6d3f80,
0xbf6dbf35,0xbec4bf35,0x3f6d3f35,0x3ec43f35,0xbef10000,0xbf62bf80,0x3f753f35,0x3e953f35,0xbf7fbf55,0xbdc9bf0e,0x3f463f7b,0xbf22be48,
0xbf22bf6d,0x3f463ec4,0xbdc93ec4,0xbf7fbf6d,0x3e95be48,0x3f753f7b,0xbf62bf0e,0xbef1bf55,0xbf55bf80,0x3f0e8000,0xbf0e0000,0xbf55bf80,
0x3e48bec4,0x3f7b3f6d,0xbf7bbf6d,0x3e48bec4,0x3f7b3f35,0x3e483f35,0xbe48bf35,0x3f7b3f35,0x3f0e3f6d,0xbf55bec4,0x3f553ec4,0x3f0e3f6d,
0x3f220000,0x3f463f80,0xbdc9bf35,0x3f7f3f35,0x3f623f7b,0xbef13e48,0x3f753f0e,0x3e953f55,0xbe953ec4,0xbf75bf6d,0x3ef13f6d,0xbf62bec4,
0xbf7fbf55,0x3dc9bf0e,0xbf46be48,0xbf22bf7b,0x3f353f80,0xbf358000,0x3f353f80,0xbf358000,0xbf350000,0xbf35bf80,0xbf350000,0xbf35bf80,
0xbf35bf80,0x3f358000,0xbf35bf80,0x3f358000,0x3f350000,0x3f353f80,0x3f350000,0x3f353f80,0xbf460000,0xbf22bf80,0xbf7fbf35,0x3dc9bf35,
0xbef1bf7b,0x3f623e48,0x3e95bf0e,0x3f753f55,0x3f753ec4,0x3e953f6d,0x3f623f6d,0xbef13ec4,0x3dc93f55,0xbf7fbf0e,0xbf223e48,0xbf46bf7b,
0xbf0ebf80,0x3f558000,0x3f550000,0x3f0e3f80,0x3f7b3ec4,0x3e483f6d,0x3e483f6d,0xbf7bbec4,0xbe483f35,0xbf7bbf35,0xbf7bbf35,0x3e48bf35,
0xbf55bf6d,0x3f0ebec4,0x3f0ebec4,0x3f553f6d,0x3f620000,0x3ef13f80,0xbe953f35,0xbf75bf35,0xbdc93f55,0xbf7fbf0e,0xbf22bf7b,0x3f46be48,
0xbf46bf6d,0x3f22bec4,0x3f7f3ec4,0x3dc93f6d,0x3f753e48,0x3e953f7b,0xbef13f0e,0xbf62bf55,0x3ec43f80,0xbf6d8000,0xbec4bf80,0x3f6d8000,
0xbf6dbf35,0x3ec4bf35,0x3f6d3f35,0xbec43f35,0x3f6d0000,0x3ec43f80,0xbf6d0000,0xbec4bf80,0xbec43f35,0xbf6dbf35,0x3ec4bf35,0x3f6d3f35,
0xbf750000,0xbe95bf80,0x3f623f35,0xbef13f35,0x3f22bf0e,0x3f463f55,0xbf7fbe48,0xbdc9bf7b,0xbdc93f6d,0xbf7fbec4,0x3f46bec4,0x3f223f6d,
0xbef1bf7b,0x3f62be48,0xbe953f55,0xbf75bf0e,0xbe48bf80,0x3f7b8000,0xbf7b0000,0xbe48bf80,0x3f0e3f6d,0xbf553ec4,0x3f55bec4,0x3f0e3f6d,
0xbf55bf35,0x3f0ebf35,0xbf0e3f35,0xbf55bf35,0x3f7b3ec4,0xbe483f6d,0x3e48bf6d,0x3f7b3ec4,0x3f7f0000,0x3dc93f80,0x3f22bf35,0x3f463f35,
0xbf753e48,0xbe95bf7b,0xbef13f55,0xbf62bf0e,0x3f62bec4,0x3ef13f6d,0x3e95bf6d,0x3f753ec4,0xbf463f0e,0xbf22bf55,0xbdc93f7b,0xbf7fbe48,
0x3f80,0xbf808000,0x3f80,0xbf808000,0xbf80,0x3f808000,0xbf80,0x3f808000,0x3f80,0xbf808000,0x3f80,0xbf808000,
0xbf80,0x3f808000,0xbf80,0x3f808000,0xbf7f0000,0x3dc9bf80,0xbf22bf35,0x3f46bf35,0x3f753e48,0xbe953f7b,0x3ef13f55,0xbf623f0e,
0xbf62bec4,0x3ef1bf6d,0xbe95bf6d,0x3f75bec4,0x3f463f0e,0xbf223f55,0x3dc93f7b,0xbf7f3e48,0x3e48bf80,0x3f7b8000,0x3f7b0000,0xbe483f80,
0xbf0e3f6d,0xbf55bec4,0xbf55bec4,0x3f0ebf6d,0x3f55bf35,0x3f0e3f35,0x3f0e3f35,0xbf553f35,0xbf7b3ec4,0xbe48bf6d,0xbe48bf6d,0x3f7bbec4,
0x3f750000,0xbe953f80,0xbf623f35,0xbef1bf35,0xbf22bf0e,0x3f46bf55,0x3f7fbe48,0xbdc93f7b,0x3dc93f6d,0xbf7f3ec4,0xbf46bec4,0x3f22bf6d,
0x3ef1bf7b,0x3f623e48,0x3e953f55,0xbf753f0e,0xbec43f80,0xbf6d8000,0x3ec4bf80,0x3f6d8000,0x3f6dbf35,0x3ec43f35,0xbf6d3f35,0xbec4bf35,
0xbf6d0000,0x3ec4bf80,0x3f6d0000,0xbec43f80,0x3ec43f35,0xbf6d3f35,0xbec4bf35,0x3f6dbf35,0xbf620000,0x3ef1bf80,0x3e953f35,0xbf753f35,
0x3dc93f55,0xbf7f3f0e,0x3f22bf7b,0x3f463e48,0x3f46bf6d,0x3f223ec4,0xbf7f3ec4,0x3dc9bf6d,0xbf753e48,0x3e95bf7b,0x3ef13f0e,0xbf623f55,
0x3f0ebf80,0x3f558000,0xbf550000,0x3f0ebf80,0xbf7b3ec4,0x3e48bf6d,0xbe483f6d,0xbf7b3ec4,0x3e483f35,0xbf7b3f35,0x3f7bbf35,0x3e483f35,
0x3f55bf6d,0x3f0e3ec4,0xbf0ebec4,0x3f55bf6d,0x3f460000,0xbf223f80,0x3f7fbf35,0x3dc93f35,0x3ef1bf7b,0x3f62be48,0xbe95bf0e,0x3f75bf55,
0xbf753ec4,0x3e95bf6d,0xbf623f6d,0xbef1bec4,0xbdc93f55,0xbf7f3f0e,0x3f223e48,0xbf463f7b,0xbf353f80,0xbf358000,0xbf353f80,0xbf358000,
0x3f350000,0xbf353f80,0x3f350000,0xbf353f80,0x3f35bf80,0x3f358000,0x3f35bf80,0x3f358000,0xbf350000,0x3f35bf80,0xbf350000,0x3f35bf80,
0xbf220000,0x3f46bf80,0x3dc9bf35,0x3f7fbf35,0xbf623f7b,0xbef1be48,0xbf753f0e,0x3e95bf55,0x3e953ec4,0xbf753f6d,0xbef13f6d,0xbf623ec4,
0x3f7fbf55,0x3dc93f0e,0x3f46be48,0xbf223f7b,0x3f55bf80,0x3f0e8000,0x3f0e0000,0xbf553f80,0xbe48bec4,0x3f7bbf6d,0x3f7bbf6d,0x3e483ec4,
0xbf7b3f35,0x3e48bf35,0x3e48bf35,0x3f7bbf35,0xbf0e3f6d,0xbf553ec4,0xbf553ec4,0x3f0ebf6d,0x3ef10000,0xbf623f80,0xbf753f35,0x3e95bf35,
0x3f7fbf55,0xbdc93f0e,0xbf463f7b,0xbf223e48,0x3f22bf6d,0x3f46bec4,0x3dc93ec4,0xbf7f3f6d,0xbe95be48,0x3f75bf7b,0x3f62bf0e,0xbef13f55,
0xbf6d3f80,0xbec48000,0x3f6dbf80,0x3ec48000,0xbec43f35,0xbf6d3f35,0x3ec4bf35,0x3f6dbf35,0x3ec40000,0xbf6d3f80,0xbec40000,0x3f6dbf80,
0x3f6dbf35,0xbec43f35,0xbf6d3f35,0x3ec4bf35,0xbe950000,0x3f75bf80,0xbef13f35,0xbf623f35,0xbf463f0e,0x3f22bf55,0x3dc93e48,0xbf7f3f7b,
0xbf7f3f6d,0x3dc9bec4,0x3f22bec4,0xbf463f6d,0xbf623f7b,0xbef13e48,0x3f75bf55,0xbe953f0e,0x3f7bbf80,0x3e488000,0xbe480000,0x3f7bbf80,
0x3f55bf6d,0x3f0ebec4,0xbf0e3ec4,0x3f55bf6d,0x3f0ebf35,0x3f55bf35,0xbf553f35,0x3f0ebf35,0x3e48bec4,0x3f7bbf6d,0xbf7b3f6d,0x3e48bec4,
0x3dc90000,0xbf7f3f80,0x3f46bf35,0xbf223f35,0x3e95be48,0xbf753f7b,0x3f62bf55,0xbef13f0e,0x3ef1bec4,0xbf623f6d,0x3f75bf6d,0xbe953ec4,
0x3f22bf0e,0xbf463f55,0x3f7fbf7b,0xbdc93e48,0x3f803f80,0xbf803f80,0x3f803f80,0xbf803f80,0x3f803f80,0xbf803f80,0x3f803f80,0xbf803f80,
0x3f803f80,0xbf803f80,0x3f803f80,0xbf803f80,0x3f803f80,0xbf803f80,0x3f803f80,0xbf803f80,0xbf7fbf80,0x3dc98000,0xbf22bf35,0x3f463f35,
0xbf75bf7b,0x3e953e48,0xbef1bf0e,0x3f623f55,0xbf62bf6d,0x3ef13ec4,0xbe95bec4,0x3f753f6d,0xbf46bf55,0x3f223f0e,0xbdc9be48,0x3f7f3f7b,
0x3f7b3f80,0xbe488000,0xbe480000,0xbf7bbf80,0x3f553f6d,0xbf0ebec4,0xbf0ebec4,0xbf55bf6d,0x3f0e3f35,0xbf55bf35,0xbf55bf35,0xbf0ebf35,
0x3e483ec4,0xbf7bbf6d,0xbf7bbf6d,0xbe48bec4,0xbf75bf80,0x3e958000,0x3f623f35,0x3ef13f35,0xbf22bf55,0x3f463f0e,0x3f7f3f7b,0xbdc93e48,
0xbdc9bec4,0x3f7f3f6d,0x3f463f6d,0xbf22bec4,0x3ef13e48,0x3f623f7b,0x3e953f0e,0xbf75bf55,0x3f6d3f80,0xbec48000,0xbf6dbf80,0x3ec48000,
0x3ec43f35,0xbf6dbf35,0xbec4bf35,0x3f6d3f35,0xbec40000,0xbf6dbf80,0x3ec40000,0x3f6d3f80,0xbf6dbf35,0xbec4bf35,0x3f6d3f35,0x3ec43f35,
0xbf62bf80,0x3ef18000,0x3e953f35,0xbf75bf35,0xbdc9bf0e,0x3f7f3f55,0xbf22be48,0xbf46bf7b,0x3f463ec4,0x3f223f6d,0xbf7fbf6d,0x3dc9bec4,
0x3f753f7b,0xbe953e48,0xbef1bf55,0x3f623f0e,0x3f553f80,0xbf0e8000,0x3f0e0000,0x3f553f80,0xbe483ec4,0xbf7bbf6d,0x3f7b3f6d,0xbe483ec4,
0xbf7bbf35,0xbe48bf35,0x3e483f35,0xbf7bbf35,0xbf0ebf6d,0x3f553ec4,0xbf55bec4,0xbf0ebf6d,0xbf46bf80,0x3f228000,0xbf7fbf35,0xbdc9bf35,
0x3ef1be48,0x3f623f7b,0xbe95bf55,0x3f753f0e,0x3f753f6d,0xbe953ec4,0x3f623ec4,0x3ef13f6d,0xbdc93f0e,0xbf7fbf55,0x3f223f7b,0xbf46be48,
0x3f353f80,0xbf358000,0x3f353f80,0xbf358000,0xbf350000,0xbf35bf80,0xbf350000,0xbf35bf80,0xbf35bf80,0x3f358000,0xbf35bf80,0x3f358000,
0x3f350000,0x3f353f80,0x3f350000,0x3f353f80,0xbf22bf80,0x3f468000,0x3dc9bf35,0x3f7f3f35,0x3f623e48,0x3ef13f7b,0x3f753f55,0xbe953f0e,
0x3e953f6d,0xbf75bec4,0xbef13ec4,0xbf62bf6d,0xbf7fbf0e,0xbdc9bf55,0xbf46bf7b,0x3f22be48,0x3f0e3f80,0xbf558000,0xbf550000,0xbf0ebf80,
0xbf7bbec4,0xbe48bf6d,0xbe48bf6d,0x3f7b3ec4,0x3e48bf35,0x3f7b3f35,0x3f7b3f35,0xbe483f35,0x3f553f6d,0xbf0e3ec4,0xbf0e3ec4,0xbf55bf6d,
0xbef1bf80,0x3f628000,0x3f753f35,0xbe953f35,0x3f7f3f0e,0xbdc93f55,0xbf463e48,0xbf22bf7b,0xbf223ec4,0xbf46bf6d,0xbdc9bf6d,0x3f7f3ec4,
0xbe95bf7b,0x3f753e48,0x3f623f55,0xbef13f0e,0x3ec43f80,0xbf6d8000,0xbec4bf80,0x3f6d8000,0xbf6dbf35,0x3ec4bf35,0x3f6d3f35,0xbec43f35,
0x3f6d0000,0x3ec43f80,0xbf6d0000,0xbec4bf80,0xbec43f35,0xbf6dbf35,0x3ec4bf35,0x3f6d3f35,0xbe95bf80,0x3f758000,0xbef13f35,0xbf62bf35,
0x3f463f55,0xbf223f0e,0xbdc9bf7b,0x3f7f3e48,0xbf7fbec4,0x3dc9bf6d,0x3f223f6d,0xbf463ec4,0x3f62be48,0x3ef13f7b,0xbf75bf0e,0x3e95bf55,
0x3e483f80,0xbf7b8000,0x3f7b0000,0x3e483f80,0xbf0ebf6d,0x3f55bec4,0xbf553ec4,0xbf0ebf6d,0x3f553f35,0xbf0e3f35,0x3f0ebf35,0x3f553f35,
0xbf7bbec4,0x3e48bf6d,0xbe483f6d,0xbf7bbec4,0xbdc9bf80,0x3f7f8000,0xbf46bf35,0x3f22bf35,0x3e953f7b,0xbf753e48,0x3f623f0e,0xbef13f55,
0xbef1bf6d,0x3f62bec4,0xbf75bec4,0x3e95bf6d,0x3f223f55,0xbf463f0e,0x3f7f3e48,0xbdc93f7b,0x3f80,0xbf808000,0x3f80,0xbf808000,
0xbf80,0x3f808000,0xbf80,0x3f808000,0x3f80,0xbf808000,0x3f80,0xbf808000,0xbf80,0x3f808000,0xbf80,0x3f808000,
0x3dc9bf80,0x3f7f8000,0x3f46bf35,0x3f223f35,0xbe953f7b,0xbf75be48,0xbf623f0e,0xbef1bf55,0x3ef1bf6d,0x3f623ec4,0x3f75bec4,0x3e953f6d,
0xbf223f55,0xbf46bf0e,0xbf7f3e48,0xbdc9bf7b,0xbe483f80,0xbf7b8000,0xbf7b0000,0x3e48bf80,0x3f0ebf6d,0x3f553ec4,0x3f553ec4,0xbf0e3f6d,
0xbf553f35,0xbf0ebf35,0xbf0ebf35,0x3f55bf35,0x3f7bbec4,0x3e483f6d,0x3e483f6d,0xbf7b3ec4,0x3e95bf80,0x3f758000,0x3ef13f35,0xbf623f35,
0xbf463f55,0xbf22bf0e,0x3dc9bf7b,0x3f7fbe48,0x3f7fbec4,0x3dc93f6d,0xbf223f6d,0xbf46bec4,0xbf62be48,0x3ef1bf7b,0x3f75bf0e,0x3e953f55,
0xbec43f80,0xbf6d8000,0x3ec4bf80,0x3f6d8000,0x3f6dbf35,0x3ec43f35,0xbf6d3f35,0xbec4bf35,0xbf6d0000,0x3ec4bf80,0x3f6d0000,0xbec43f80,
0x3ec43f35,0xbf6d3f35,0xbec4bf35,0x3f6dbf35,0x3ef1bf80,0x3f628000,0xbf753f35,0xbe95bf35,0xbf7f3f0e,0xbdc9bf55,0x3f463e48,0xbf223f7b,
0x3f223ec4,0xbf463f6d,0x3dc9bf6d,0x3f7fbec4,0x3e95bf7b,0x3f75be48,0xbf623f55,0xbef1bf0e,0xbf0e3f80,0xbf558000,0x3f550000,0xbf0e3f80,
0x3f7bbec4,0xbe483f6d,0x3e48bf6d,0x3f7bbec4,0xbe48bf35,0x3f7bbf35,0xbf7b3f35,0xbe48bf35,0xbf553f6d,0xbf0ebec4,0x3f0e3ec4,0xbf553f6d,
0x3f22bf80,0x3f468000,0xbdc9bf35,0x3f7fbf35,0xbf623e48,0x3ef1bf7b,0xbf753f55,0xbe95bf0e,0xbe953f6d,0xbf753ec4,0x3ef13ec4,0xbf623f6d,
0x3f7fbf0e,0xbdc93f55,0x3f46bf7b,0x3f223e48,0xbf353f80,0xbf358000,0xbf353f80,0xbf358000,0x3f350000,0xbf353f80,0x3f350000,0xbf353f80,
0x3f35bf80,0x3f358000,0x3f35bf80,0x3f358000,0xbf350000,0x3f35bf80,0xbf350000,0x3f35bf80,0x3f46bf80,0x3f228000,0x3f7fbf35,0xbdc93f35,
0xbef1be48,0x3f62bf7b,0x3e95bf55,0x3f75bf0e,0xbf753f6d,0xbe95bec4,0xbf623ec4,0x3ef1bf6d,0x3dc93f0e,0xbf7f3f55,0xbf223f7b,0xbf463e48,
0xbf553f80,0xbf0e8000,0xbf0e0000,0x3f55bf80,0x3e483ec4,0xbf7b3f6d,0xbf7b3f6d,0xbe48bec4,0x3f7bbf35,0xbe483f35,0xbe483f35,0xbf7b3f35,
0x3f0ebf6d,0x3f55bec4,0x3f55bec4,0xbf0e3f6d,0x3f62bf80,0x3ef18000,0xbe953f35,0xbf753f35,0x3dc9bf0e,0x3f7fbf55,0x3f22be48,0xbf463f7b,
0xbf463ec4,0x3f22bf6d,0x3f7fbf6d,0x3dc93ec4,0xbf753f7b,0xbe95be48,0x3ef1bf55,0x3f62bf0e,0xbf6d3f80,0xbec48000,0x3f6dbf80,0x3ec48000,
0xbec43f35,0xbf6d3f35,0x3ec4bf35,0x3f6dbf35,0x3ec40000,0xbf6d3f80,0xbec40000,0x3f6dbf80,0x3f6dbf35,0xbec43f35,0xbf6d3f35,0x3ec4bf35,
0x3f75bf80,0x3e958000,0xbf623f35,0x3ef1bf35,0x3f22bf55,0x3f46bf0e,0xbf7f3f7b,0xbdc9be48,0x3dc9bec4,0x3f7fbf6d,0xbf463f6d,0xbf223ec4,
0xbef13e48,0x3f62bf7b,0xbe953f0e,0xbf753f55,0xbf7b3f80,0xbe488000,0x3e480000,0xbf7b3f80,0xbf553f6d,0xbf0e3ec4,0x3f0ebec4,0xbf553f6d,
0xbf0e3f35,0xbf553f35,0x3f55bf35,0xbf0e3f35,0xbe483ec4,0xbf7b3f6d,0x3f7bbf6d,0xbe483ec4,0x3f7fbf80,0x3dc98000,0x3f22bf35,0x3f46bf35,
0x3f75bf7b,0x3e95be48,0x3ef1bf0e,0x3f62bf55,0x3f62bf6d,0x3ef1bec4,0x3e95bec4,0x3f75bf6d,0x3f46bf55,0x3f22bf0e,0x3dc9be48,0x3f7fbf7b,
0x3f803f80,0xbf803f80,0x3f803f80,0xbf803f80,0x3f803f80,0xbf803f80,0x3f803f80,0xbf803f80,0x3f803f80,0xbf803f80,0x3f803f80,0xbf803f80,
0x3f803f80,0xbf803f80,0x3f803f80,0xbf803f80,0x3dc90000,0x3f7f3f80,0x3f463f35,0x3f223f35,0x3e953e48,0x3f753f7b,0x3f623f55,0x3ef13f0e,
0x3ef13ec4,0x3f623f6d,0x3f753f6d,0x3e953ec4,0x3f223f0e,0x3f463f55,0x3f7f3f7b,0x3dc93e48,0xbf7bbf80,0x3e488000,0x3e480000,0x3f7b3f80,
0xbf55bf6d,0x3f0e3ec4,0x3f0e3ec4,0x3f553f6d,0xbf0ebf35,0x3f553f35,0x3f553f35,0x3f0e3f35,0xbe48bec4,0x3f7b3f6d,0x3f7b3f6d,0x3e483ec4,
0xbe950000,0xbf75bf80,0xbef1bf35,0x3f623f35,0xbf46bf0e,0xbf22bf55,0x3dc9be48,0x3f7f3f7b,0xbf7fbf6d,0xbdc9bec4,0x3f223ec4,0x3f463f6d,
0xbf62bf7b,0x3ef13e48,0x3f753f55,0x3e953f0e,0x3f6d3f80,0xbec48000,0xbf6dbf80,0x3ec48000,0x3ec43f35,0xbf6dbf35,0xbec4bf35,0x3f6d3f35,
0xbec40000,0xbf6dbf80,0x3ec40000,0x3f6d3f80,0xbf6dbf35,0xbec4bf35,0x3f6d3f35,0x3ec43f35,0x3ef10000,0x3f623f80,0xbf75bf35,0xbe95bf35,
0x3f7f3f55,0x3dc93f0e,0xbf46bf7b,0x3f223e48,0x3f223f6d,0xbf46bec4,0x3dc9bec4,0x3f7f3f6d,0xbe953e48,0xbf75bf7b,0x3f623f0e,0x3ef13f55,
0xbf55bf80,0x3f0e8000,0xbf0e0000,0xbf55bf80,0x3e48bec4,0x3f7b3f6d,0xbf7bbf6d,0x3e48bec4,0x3f7b3f35,0x3e483f35,0xbe48bf35,0x3f7b3f35,
0x3f0e3f6d,0xbf55bec4,0x3f553ec4,0x3f0e3f6d,0xbf220000,0xbf46bf80,0x3dc93f35,0xbf7fbf35,0xbf62bf7b,0x3ef1be48,0xbf75bf0e,0xbe95bf55,
0x3e95bec4,0x3f753f6d,0xbef1bf6d,0x3f623ec4,0x3f7f3f55,0xbdc93f0e,0x3f463e48,0x3f223f7b,0x3f353f80,0xbf358000,0x3f353f80,0xbf358000,
0xbf350000,0xbf35bf80,0xbf350000,0xbf35bf80,0xbf35bf80,0x3f358000,0xbf35bf80,0x3f358000,0x3f350000,0x3f353f80,0x3f350000,0x3f353f80,
0x3f460000,0x3f223f80,0x3f7f3f35,0xbdc93f35,0x3ef13f7b,0xbf62be48,0xbe953f0e,0xbf75bf55,0xbf75bec4,0xbe95bf6d,0xbf62bf6d,0x3ef1bec4,
0xbdc9bf55,0x3f7f3f0e,0x3f22be48,0x3f463f7b,0xbf0ebf80,0x3f558000,0x3f550000,0x3f0e3f80,0x3f7b3ec4,0x3e483f6d,0x3e483f6d,0xbf7bbec4,
0xbe483f35,0xbf7bbf35,0xbf7bbf35,0x3e48bf35,0xbf55bf6d,0x3f0ebec4,0x3f0ebec4,0x3f553f6d,0xbf620000,0xbef1bf80,0x3e95bf35,0x3f753f35,
0x3dc9bf55,0x3f7f3f0e,0x3f223f7b,0xbf463e48,0x3f463f6d,0xbf223ec4,0xbf7fbec4,0xbdc9bf6d,0xbf75be48,0xbe95bf7b,0x3ef1bf0e,0x3f623f55,
0x3ec43f80,0xbf6d8000,0xbec4bf80,0x3f6d8000,0xbf6dbf35,0x3ec4bf35,0x3f6d3f35,0xbec43f35,0x3f6d0000,0x3ec43f80,0xbf6d0000,0xbec4bf80,
0xbec43f35,0xbf6dbf35,0x3ec4bf35,0x3f6d3f35,0x3f750000,0x3e953f80,0xbf62bf35,0x3ef1bf35,0xbf223f0e,0xbf46bf55,0x3f7f3e48,0x3dc93f7b,
0x3dc9bf6d,0x3f7f3ec4,0xbf463ec4,0xbf22bf6d,0x3ef13f7b,0xbf623e48,0x3e95bf55,0x3f753f0e,0xbe48bf80,0x3f7b8000,0xbf7b0000,0xbe48bf80,
0x3f0e3f6d,0xbf553ec4,0x3f55bec4,0x3f0e3f6d,0xbf55bf35,0x3f0ebf35,0xbf0e3f35,0xbf55bf35,0x3f7b3ec4,0xbe483f6d,0x3e48bf6d,0x3f7b3ec4,
0xbf7f0000,0xbdc9bf80,0xbf223f35,0xbf46bf35,0x3f75be48,0x3e953f7b,0x3ef1bf55,0x3f623f0e,0xbf623ec4,0xbef1bf6d,0xbe953f6d,0xbf75bec4,
0x3f46bf0e,0x3f223f55,0x3dc9bf7b,0x3f7f3e48,0x3f80,0xbf808000,0x3f80,0xbf808000,0xbf80,0x3f808000,0xbf80,0x3f808000,
0x3f80,0xbf808000,0x3f80,0xbf808000,0xbf80,0x3f808000,0xbf80,0x3f808000,0x3f7f0000,0xbdc93f80,0x3f223f35,0xbf463f35,
0xbf75be48,0x3e95bf7b,0xbef1bf55,0x3f62bf0e,0x3f623ec4,0xbef13f6d,0x3e953f6d,0xbf753ec4,0xbf46bf0e,0x3f22bf55,0xbdc9bf7b,0x3f7fbe48,
0x3e48bf80,0x3f7b8000,0x3f7b0000,0xbe483f80,0xbf0e3f6d,0xbf55bec4,0xbf55bec4,0x3f0ebf6d,0x3f55bf35,0x3f0e3f35,0x3f0e3f35,0xbf553f35,
0xbf7b3ec4,0xbe48bf6d,0xbe48bf6d,0x3f7bbec4,0xbf750000,0x3e95bf80,0x3f62bf35,0x3ef13f35,0x3f223f0e,0xbf463f55,0xbf7f3e48,0x3dc9bf7b,
0xbdc9bf6d,0x3f7fbec4,0x3f463ec4,0xbf223f6d,0xbef13f7b,0xbf62be48,0xbe95bf55,0x3f75bf0e,0xbec43f80,0xbf6d8000,0x3ec4bf80,0x3f6d8000,
0x3f6dbf35,0x3ec43f35,0xbf6d3f35,0xbec4bf35,0xbf6d0000,0x3ec4bf80,0x3f6d0000,0xbec43f80,0x3ec43f35,0xbf6d3f35,0xbec4bf35,0x3f6dbf35,
0x3f620000,0xbef13f80,0xbe95bf35,0x3f75bf35,0xbdc9bf55,0x3f7fbf0e,0xbf223f7b,0xbf46be48,0xbf463f6d,0xbf22bec4,0x3f7fbec4,0xbdc93f6d,
0x3f75be48,0xbe953f7b,0xbef1bf0e,0x3f62bf55,0x3f0ebf80,0x3f558000,0xbf550000,0x3f0ebf80,0xbf7b3ec4,0x3e48bf6d,0xbe483f6d,0xbf7b3ec4,
0x3e483f35,0xbf7b3f35,0x3f7bbf35,0x3e483f35,0x3f55bf6d,0x3f0e3ec4,0xbf0ebec4,0x3f55bf6d,0xbf460000,0x3f22bf80,0xbf7f3f35,0xbdc9bf35,
0xbef13f7b,0xbf623e48,0x3e953f0e,0xbf753f55,0x3f75bec4,0xbe953f6d,0x3f62bf6d,0x3ef13ec4,0x3dc9bf55,0x3f7fbf0e,0xbf22be48,0x3f46bf7b,
0xbf353f80,0xbf358000,0xbf353f80,0xbf358000,0x3f350000,0xbf353f80,0x3f350000,0xbf353f80,0x3f35bf80,0x3f358000,0x3f35bf80,0x3f358000,
0xbf350000,0x3f35bf80,0xbf350000,0x3f35bf80,0x3f220000,0xbf463f80,0xbdc93f35,0xbf7f3f35,0x3f62bf7b,0x3ef13e48,0x3f75bf0e,0xbe953f55,
0xbe95bec4,0x3f75bf6d,0x3ef1bf6d,0x3f62bec4,0xbf7f3f55,0xbdc9bf0e,0xbf463e48,0x3f22bf7b,0x3f55bf80,0x3f0e8000,0x3f0e0000,0xbf553f80,
0xbe48bec4,0x3f7bbf6d,0x3f7bbf6d,0x3e483ec4,0xbf7b3f35,0x3e48bf35,0x3e48bf35,0x3f7bbf35,0xbf0e3f6d,0xbf553ec4,0xbf553ec4,0x3f0ebf6d,
0xbef10000,0x3f62bf80,0x3f75bf35,0xbe953f35,0xbf7f3f55,0x3dc9bf0e,0x3f46bf7b,0x3f22be48,0xbf223f6d,0xbf463ec4,0xbdc9bec4,0x3f7fbf6d,
0x3e953e48,0xbf753f7b,0xbf623f0e,0x3ef1bf55,0xbf6d3f80,0xbec48000,0x3f6dbf80,0x3ec48000,0xbec43f35,0xbf6d3f35,0x3ec4bf35,0x3f6dbf35,
0x3ec40000,0xbf6d3f80,0xbec40000,0x3f6dbf80,0x3f6dbf35,0xbec43f35,0xbf6d3f35,0x3ec4bf35,0x3e950000,0xbf753f80,0x3ef1bf35,0x3f62bf35,
0x3f46bf0e,0xbf223f55,0xbdc9be48,0x3f7fbf7b,0x3f7fbf6d,0xbdc93ec4,0xbf223ec4,0x3f46bf6d,0x3f62bf7b,0x3ef1be48,0xbf753f55,0x3e95bf0e,
0x3f7bbf80,0x3e488000,0xbe480000,0x3f7bbf80,0x3f55bf6d,0x3f0ebec4,0xbf0e3ec4,0x3f55bf6d,0x3f0ebf35,0x3f55bf35,0xbf553f35,0x3f0ebf35,
0x3e48bec4,0x3f7bbf6d,0xbf7b3f6d,0x3e48bec4,0xbdc90000,0x3f7fbf80,0xbf463f35,0x3f22bf35,0xbe953e48,0x3f75bf7b,0xbf623f55,0x3ef1bf0e,
0xbef13ec4,0x3f62bf6d,0xbf753f6d,0x3e95bec4,0xbf223f0e,0x3f46bf55,0xbf7f3f7b,0x3dc9be48,0x3f803f80,0x3f803f80,0x3f803f80,0x3f803f80,
0x3f803f80,0x3f803f80,0x3f803f80,0x3f803f80,0x3f803f80,0x3f803f80,0x3f803f80,0x3f803f80,0x3f803f80,0x3f803f80,0x3f803f80,0x3f803f80,
0x0,0x0,0x0,0x0,0x0,0x0,0x0,0x0,0x0,0x0,0x0,0x0,
0x0,0x0,0x0,0x0,0xbe480000,0xbf0ebec4,0xbf55bf35,0xbf7bbf6d,0x3f7b3f80,0x3f553f6d,0x3f0e3f35,0x3e483ec4,
0x3e480000,0x3f0e3ec4,0x3f553f35,0x3f7b3f6d,0xbf7bbf80,0xbf55bf6d,0xbf0ebf35,0xbe48bec4,0x3f7b3f80,0x3f553f6d,0x3f0e3f35,0x3e483ec4,
0x3e480000,0x3f0e3ec4,0x3f553f35,0x3f7b3f6d,0xbf7bbf80,0xbf55bf6d,0xbf0ebf35,0xbe48bec4,0xbe480000,0xbf0ebec4,0xbf55bf35,0xbf7bbf6d,
0x3f6d3f80,0x3ec43f35,0xbec40000,0xbf6dbf35,0xbf6dbf80,0xbec4bf35,0x3ec40000,0x3f6d3f35,0x3f6d3f80,0x3ec43f35,0xbec40000,0xbf6dbf35,
0xbf6dbf80,0xbec4bf35,0x3ec40000,0x3f6d3f35,0x3ec40000,0x3f6d3f35,0x3f6d3f80,0x3ec43f35,0xbec40000,0xbf6dbf35,0xbf6dbf80,0xbec4bf35,
0x3ec40000,0x3f6d3f35,0x3f6d3f80,0x3ec43f35,0xbec40000,0xbf6dbf35,0xbf6dbf80,0xbec4bf35,0xbf0e0000,0xbf7bbf6d,0xbe48bf35,0x3f553ec4,
0xbf55bf80,0x3e48bec4,0x3f7b3f35,0x3f0e3f6d,0x3f0e0000,0x3f7b3f6d,0x3e483f35,0xbf55bec4,0x3f553f80,0xbe483ec4,0xbf7bbf35,0xbf0ebf6d,
0x3f553f80,0xbe483ec4,0xbf7bbf35,0xbf0ebf6d,0xbf0e0000,0xbf7bbf6d,0xbe48bf35,0x3f553ec4,0xbf55bf80,0x3e48bec4,0x3f7b3f35,0x3f0e3f6d,
0x3f0e0000,0x3f7b3f6d,0x3e483f35,0xbf55bec4,0x3f350000,0x3f353f80,0xbf350000,0xbf35bf80,0x3f350000,0x3f353f80,0xbf350000,0xbf35bf80,
0x3f350000,0x3f353f80,0xbf350000,0xbf35bf80,0x3f350000,0x3f353f80,0xbf350000,0xbf35bf80,0x3f353f80,0xbf350000,0xbf35bf80,0x3f350000,
0x3f353f80,0xbf350000,0xbf35bf80,0x3f350000,0x3f353f80,0xbf350000,0xbf35bf80,0x3f350000,0x3f353f80,0xbf350000,0xbf35bf80,0x3f350000,
0x3f0e3f80,0xbf7bbec4,0x3e48bf35,0x3f553f6d,0x3f550000,0x3e483f6d,0xbf7bbf35,0x3f0ebec4,0xbf0ebf80,0x3f7b3ec4,0xbe483f35,0xbf55bf6d,
0xbf550000,0xbe48bf6d,0x3f7b3f35,0xbf0e3ec4,0xbf550000,0xbe48bf6d,0x3f7b3f35,0xbf0e3ec4,0x3f0e3f80,0xbf7bbec4,0x3e48bf35,0x3f553f6d,
0x3f550000,0x3e483f6d,0xbf7bbf35,0x3f0ebec4,0xbf0ebf80,0x3f7b3ec4,0xbe483f35,0xbf55bf6d,0x3f6d0000,0xbec43f35,0xbec4bf80,0x3f6d3f35,
0xbf6d0000,0x3ec4bf35,0x3ec43f80,0xbf6dbf35,0x3f6d0000,0xbec43f35,0xbec4bf80,0x3f6d3f35,0xbf6d0000,0x3ec4bf35,0x3ec43f80,0xbf6dbf35,
0x3ec43f80,0xbf6dbf35,0x3f6d0000,0xbec43f35,0xbec4bf80,0x3f6d3f35,0xbf6d0000,0x3ec4bf35,0x3ec43f80,0xbf6dbf35,0x3f6d0000,0xbec43f35,
0xbec4bf80,0x3f6d3f35,0xbf6d0000,0x3ec4bf35,0x3e483f80,0xbf0ebf6d,0x3f553f35,0xbf7bbec4,0xbf7b0000,0x3f55bec4,0xbf0e3f35,0x3e48bf6d,
0xbe48bf80,0x3f0e3f6d,0xbf55bf35,0x3f7b3ec4,0x3f7b0000,0xbf553ec4,0x3f0ebf35,0xbe483f6d,0xbf7b0000,0x3f55bec4,0xbf0e3f35,0x3e48bf6d,
0xbe48bf80,0x3f0e3f6d,0xbf55bf35,0x3f7b3ec4,0x3f7b0000,0xbf553ec4,0x3f0ebf35,0xbe483f6d,0x3e483f80,0xbf0ebf6d,0x3f553f35,0xbf7bbec4,
0x3f80,0xbf80,0x3f80,0xbf80,0x3f80,0xbf80,0x3f80,0xbf80,0x3f80,0xbf80,0x3f80,0xbf80,
0x3f80,0xbf80,0x3f80,0xbf80,0x3f800000,0xbf800000,0x3f800000,0xbf800000,0x3f800000,0xbf800000,0x3f800000,0xbf800000,
0x3f800000,0xbf800000,0x3f800000,0xbf800000,0x3f800000,0xbf800000,0x3f800000,0xbf800000,0xbf7b0000,0x3f553ec4,0xbf0ebf35,0x3e483f6d,
0xbe483f80,0x3f0ebf6d,0xbf553f35,0x3f7bbec4,0x3f7b0000,0xbf55bec4,0x3f0e3f35,0xbe48bf6d,0x3e48bf80,0xbf0e3f6d,0x3f55bf35,0xbf7b3ec4,
0xbe483f80,0x3f0ebf6d,0xbf553f35,0x3f7bbec4,0x3f7b0000,0xbf55bec4,0x3f0e3f35,0xbe48bf6d,0x3e48bf80,0xbf0e3f6d,0x3f55bf35,0xbf7b3ec4,
0xbf7b0000,0x3f553ec4,0xbf0ebf35,0x3e483f6d,0xbec43f80,0x3f6dbf35,0xbf6d0000,0x3ec43f35,0x3ec4bf80,0xbf6d3f35,0x3f6d0000,0xbec4bf35,
0xbec43f80,0x3f6dbf35,0xbf6d0000,0x3ec43f35,0x3ec4bf80,0xbf6d3f35,0x3f6d0000,0xbec4bf35,0x3f6d0000,0xbec4bf35,0xbec43f80,0x3f6dbf35,
0xbf6d0000,0x3ec43f35,0x3ec4bf80,0xbf6d3f35,0x3f6d0000,0xbec4bf35,0xbec43f80,0x3f6dbf35,0xbf6d0000,0x3ec43f35,0x3ec4bf80,0xbf6d3f35,
0xbf550000,0xbe483f6d,0x3f7bbf35,0xbf0ebec4,0x3f0ebf80,0xbf7b3ec4,0x3e483f35,0x3f55bf6d,0x3f550000,0x3e48bf6d,0xbf7b3f35,0x3f0e3ec4,
0xbf0e3f80,0x3f7bbec4,0xbe48bf35,0xbf553f6d,0xbf0e3f80,0x3f7bbec4,0xbe48bf35,0xbf553f6d,0xbf550000,0xbe483f6d,0x3f7bbf35,0xbf0ebec4,
0x3f0ebf80,0xbf7b3ec4,0x3e483f35,0x3f55bf6d,0x3f550000,0x3e48bf6d,0xbf7b3f35,0x3f0e3ec4,0x3f350000,0x3f35bf80,0xbf350000,0xbf353f80,
0x3f350000,0x3f35bf80,0xbf350000,0xbf353f80,0x3f350000,0x3f35bf80,0xbf350000,0xbf353f80,0x3f350000,0x3f35bf80,0xbf350000,0xbf353f80,
0xbf353f80,0x3f350000,0x3f35bf80,0xbf350000,0xbf353f80,0x3f350000,0x3f35bf80,0xbf350000,0xbf353f80,0x3f350000,0x3f35bf80,0xbf350000,
0xbf353f80,0x3f350000,0x3f35bf80,0xbf350000,0xbf553f80,0x3e483ec4,0x3f7bbf35,0x3f0ebf6d,0x3f0e0000,0x3f7bbf6d,0x3e48bf35,0xbf553ec4,
0x3f55bf80,0xbe48bec4,0xbf7b3f35,0xbf0e3f6d,0xbf0e0000,0xbf7b3f6d,0xbe483f35,0x3f55bec4,0xbf0e0000,0xbf7b3f6d,0xbe483f35,0x3f55bec4,
0xbf553f80,0x3e483ec4,0x3f7bbf35,0x3f0ebf6d,0x3f0e0000,0x3f7bbf6d,0x3e48bf35,0xbf553ec4,0x3f55bf80,0xbe48bec4,0xbf7b3f35,0xbf0e3f6d,
0x3ec40000,0x3f6dbf35,0x3f6dbf80,0x3ec4bf35,0xbec40000,0xbf6d3f35,0xbf6d3f80,0xbec43f35,0x3ec40000,0x3f6dbf35,0x3f6dbf80,0x3ec4bf35,
0xbec40000,0xbf6d3f35,0xbf6d3f80,0xbec43f35,0xbf6d3f80,0xbec43f35,0x3ec40000,0x3f6dbf35,0x3f6dbf80,0x3ec4bf35,0xbec40000,0xbf6d3f35,
0xbf6d3f80,0xbec43f35,0x3ec40000,0x3f6dbf35,0x3f6dbf80,0x3ec4bf35,0xbec40000,0xbf6d3f35,0xbf7b3f80,0xbf553f6d,0xbf0e3f35,0xbe483ec4,
0xbe480000,0xbf0e3ec4,0xbf553f35,0xbf7b3f6d,0x3f7bbf80,0x3f55bf6d,0x3f0ebf35,0x3e48bec4,0x3e480000,0x3f0ebec4,0x3f55bf35,0x3f7bbf6d,
0xbe480000,0xbf0e3ec4,0xbf553f35,0xbf7b3f6d,0x3f7bbf80,0x3f55bf6d,0x3f0ebf35,0x3e48bec4,0x3e480000,0x3f0ebec4,0x3f55bf35,0x3f7bbf6d,
0xbf7b3f80,0xbf553f6d,0xbf0e3f35,0xbe483ec4,0xbf803f80,0xbf803f80,0xbf803f80,0xbf803f80,0xbf803f80,0xbf803f80,0xbf803f80,0xbf803f80,
0xbf803f80,0xbf803f80,0xbf803f80,0xbf803f80,0xbf803f80,0xbf803f80,0xbf803f80,0xbf803f80,0x0,0x0,0x0,0x0,
0x0,0x0,0x0,0x0,0x0,0x0,0x0,0x0,0x0,0x0,0x0,0x0,
0x3e480000,0x3f0ebec4,0x3f55bf35,0x3f7bbf6d,0xbf7b3f80,0xbf553f6d,0xbf0e3f35,0xbe483ec4,0xbe480000,0xbf0e3ec4,0xbf553f35,0xbf7b3f6d,
0x3f7bbf80,0x3f55bf6d,0x3f0ebf35,0x3e48bec4,0xbf7b3f80,0xbf553f6d,0xbf0e3f35,0xbe483ec4,0xbe480000,0xbf0e3ec4,0xbf553f35,0xbf7b3f6d,
0x3f7bbf80,0x3f55bf6d,0x3f0ebf35,0x3e48bec4,0x3e480000,0x3f0ebec4,0x3f55bf35,0x3f7bbf6d,0xbf6d3f80,0xbec43f35,0x3ec40000,0x3f6dbf35,
0x3f6dbf80,0x3ec4bf35,0xbec40000,0xbf6d3f35,0xbf6d3f80,0xbec43f35,0x3ec40000,0x3f6dbf35,0x3f6dbf80,0x3ec4bf35,0xbec40000,0xbf6d3f35,
0xbec40000,0xbf6d3f35,0xbf6d3f80,0xbec43f35,0x3ec40000,0x3f6dbf35,0x3f6dbf80,0x3ec4bf35,0xbec40000,0xbf6d3f35,0xbf6d3f80,0xbec43f35,
0x3ec40000,0x3f6dbf35,0x3f6dbf80,0x3ec4bf35,0x3f0e0000,0x3f7bbf6d,0x3e48bf35,0xbf553ec4,0x3f55bf80,0xbe48bec4,0xbf7b3f35,0xbf0e3f6d,
0xbf0e0000,0xbf7b3f6d,0xbe483f35,0x3f55bec4,0xbf553f80,0x3e483ec4,0x3f7bbf35,0x3f0ebf6d,0xbf553f80,0x3e483ec4,0x3f7bbf35,0x3f0ebf6d,
0x3f0e0000,0x3f7bbf6d,0x3e48bf35,0xbf553ec4,0x3f55bf80,0xbe48bec4,0xbf7b3f35,0xbf0e3f6d,0xbf0e0000,0xbf7b3f6d,0xbe483f35,0x3f55bec4,
0xbf350000,0xbf353f80,0x3f350000,0x3f35bf80,0xbf350000,0xbf353f80,0x3f350000,0x3f35bf80,0xbf350000,0xbf353f80,0x3f350000,0x3f35bf80,
0xbf350000,0xbf353f80,0x3f350000,0x3f35bf80,0xbf353f80,0x3f350000,0x3f35bf80,0xbf350000,0xbf353f80,0x3f350000,0x3f35bf80,0xbf350000,
0xbf353f80,0x3f350000,0x3f35bf80,0xbf350000,0xbf353f80,0x3f350000,0x3f35bf80,0xbf350000,0xbf0e3f80,0x3f7bbec4,0xbe48bf35,0xbf553f6d,
0xbf550000,0xbe483f6d,0x3f7bbf35,0xbf0ebec4,0x3f0ebf80,0xbf7b3ec4,0x3e483f35,0x3f55bf6d,0x3f550000,0x3e48bf6d,0xbf7b3f35,0x3f0e3ec4,
0x3f550000,0x3e48bf6d,0xbf7b3f35,0x3f0e3ec4,0xbf0e3f80,0x3f7bbec4,0xbe48bf35,0xbf553f6d,0xbf550000,0xbe483f6d,0x3f7bbf35,0xbf0ebec4,
0x3f0ebf80,0xbf7b3ec4,0x3e483f35,0x3f55bf6d,0xbf6d0000,0x3ec43f35,0x3ec4bf80,0xbf6d3f35,0x3f6d0000,0xbec4bf35,0xbec43f80,0x3f6dbf35,
0xbf6d0000,0x3ec43f35,0x3ec4bf80,0xbf6d3f35,0x3f6d0000,0xbec4bf35,0xbec43f80,0x3f6dbf35,0xbec43f80,0x3f6dbf35,0xbf6d0000,0x3ec43f35,
0x3ec4bf80,0xbf6d3f35,0x3f6d0000,0xbec4bf35,0xbec43f80,0x3f6dbf35,0xbf6d0000,0x3ec43f35,0x3ec4bf80,0xbf6d3f35,0x3f6d0000,0xbec4bf35,
0xbe483f80,0x3f0ebf6d,0xbf553f35,0x3f7bbec4,0x3f7b0000,0xbf55bec4,0x3f0e3f35,0xbe48bf6d,0x3e48bf80,0xbf0e3f6d,0x3f55bf35,0xbf7b3ec4,
0xbf7b0000,0x3f553ec4,0xbf0ebf35,0x3e483f6d,0x3f7b0000,0xbf55bec4,0x3f0e3f35,0xbe48bf6d,0x3e48bf80,0xbf0e3f6d,0x3f55bf35,0xbf7b3ec4,
0xbf7b0000,0x3f553ec4,0xbf0ebf35,0x3e483f6d,0xbe483f80,0x3f0ebf6d,0xbf553f35,0x3f7bbec4,0x3f80,0xbf80,0x3f80,0xbf80,
0x3f80,0xbf80,0x3f80,0xbf80,0x3f80,0xbf80,0x3f80,0xbf80,0x3f80,0xbf80,0x3f80,0xbf80,
0xbf800000,0x3f800000,0xbf800000,0x3f800000,0xbf800000,0x3f800000,0xbf800000,0x3f800000,0xbf800000,0x3f800000,0xbf800000,0x3f800000,
0xbf800000,0x3f800000,0xbf800000,0x3f800000,0x3f7b0000,0xbf553ec4,0x3f0ebf35,0xbe483f6d,0x3e483f80,0xbf0ebf6d,0x3f553f35,0xbf7bbec4,
0xbf7b0000,0x3f55bec4,0xbf0e3f35,0x3e48bf6d,0xbe48bf80,0x3f0e3f6d,0xbf55bf35,0x3f7b3ec4,0x3e483f80,0xbf0ebf6d,0x3f553f35,0xbf7bbec4,
0xbf7b0000,0x3f55bec4,0xbf0e3f35,0x3e48bf6d,0xbe48bf80,0x3f0e3f6d,0xbf55bf35,0x3f7b3ec4,0x3f7b0000,0xbf553ec4,0x3f0ebf35,0xbe483f6d,
0x3ec43f80,0xbf6dbf35,0x3f6d0000,0xbec43f35,0xbec4bf80,0x3f6d3f35,0xbf6d0000,0x3ec4bf35,0x3ec43f80,0xbf6dbf35,0x3f6d0000,0xbec43f35,
0xbec4bf80,0x3f6d3f35,0xbf6d0000,0x3ec4bf35,0xbf6d0000,0x3ec4bf35,0x3ec43f80,0xbf6dbf35,0x3f6d0000,0xbec43f35,0xbec4bf80,0x3f6d3f35,
0xbf6d0000,0x3ec4bf35,0x3ec43f80,0xbf6dbf35,0x3f6d0000,0xbec43f35,0xbec4bf80,0x3f6d3f35,0x3f550000,0x3e483f6d,0xbf7bbf35,0x3f0ebec4,
0xbf0ebf80,0x3f7b3ec4,0xbe483f35,0xbf55bf6d,0xbf550000,0xbe48bf6d,0x3f7b3f35,0xbf0e3ec4,0x3f0e3f80,0xbf7bbec4,0x3e48bf35,0x3f553f6d,
0x3f0e3f80,0xbf7bbec4,0x3e48bf35,0x3f553f6d,0x3f550000,0x3e483f6d,0xbf7bbf35,0x3f0ebec4,0xbf0ebf80,0x3f7b3ec4,0xbe483f35,0xbf55bf6d,
0xbf550000,0xbe48bf6d,0x3f7b3f35,0xbf0e3ec4,0xbf350000,0xbf35bf80,0x3f350000,0x3f353f80,0xbf350000,0xbf35bf80,0x3f350000,0x3f353f80,
0xbf350000,0xbf35bf80,0x3f350000,0x3f353f80,0xbf350000,0xbf35bf80,0x3f350000,0x3f353f80,0x3f353f80,0xbf350000,0xbf35bf80,0x3f350000,
0x3f353f80,0xbf350000,0xbf35bf80,0x3f350000,0x3f353f80,0xbf350000,0xbf35bf80,0x3f350000,0x3f353f80,0xbf350000,0xbf35bf80,0x3f350000,
0x3f553f80,0xbe483ec4,0xbf7bbf35,0xbf0ebf6d,0xbf0e0000,0xbf7bbf6d,0xbe48bf35,0x3f553ec4,0xbf55bf80,0x3e48bec4,0x3f7b3f35,0x3f0e3f6d,
0x3f0e0000,0x3f7b3f6d,0x3e483f35,0xbf55bec4,0x3f0e0000,0x3f7b3f6d,0x3e483f35,0xbf55bec4,0x3f553f80,0xbe483ec4,0xbf7bbf35,0xbf0ebf6d,
0xbf0e0000,0xbf7bbf6d,0xbe48bf35,0x3f553ec4,0xbf55bf80,0x3e48bec4,0x3f7b3f35,0x3f0e3f6d,0xbec40000,0xbf6dbf35,0xbf6dbf80,0xbec4bf35,
0x3ec40000,0x3f6d3f35,0x3f6d3f80,0x3ec43f35,0xbec40000,0xbf6dbf35,0xbf6dbf80,0xbec4bf35,0x3ec40000,0x3f6d3f35,0x3f6d3f80,0x3ec43f35,
0x3f6d3f80,0x3ec43f35,0xbec40000,0xbf6dbf35,0xbf6dbf80,0xbec4bf35,0x3ec40000,0x3f6d3f35,0x3f6d3f80,0x3ec43f35,0xbec40000,0xbf6dbf35,
0xbf6dbf80,0xbec4bf35,0x3ec40000,0x3f6d3f35,0x3f7b3f80,0x3f553f6d,0x3f0e3f35,0x3e483ec4,0x3e480000,0x3f0e3ec4,0x3f553f35,0x3f7b3f6d,
0xbf7bbf80,0xbf55bf6d,0xbf0ebf35,0xbe48bec4,0xbe480000,0xbf0ebec4,0xbf55bf35,0xbf7bbf6d,0x3e480000,0x3f0e3ec4,0x3f553f35,0x3f7b3f6d,
0xbf7bbf80,0xbf55bf6d,0xbf0ebf35,0xbe48bec4,0xbe480000,0xbf0ebec4,0xbf55bf35,0xbf7bbf6d,0x3f7b3f80,0x3f553f6d,0x3f0e3f35,0x3e483ec4,
0x80008000,0x80008000,0x80008000,0x80008000,0x80008000,0x80008000,0x80008000,0x80008000,0x80008000,0x80008000,0x80008000,0x80008000,
0x80008000,0x80008000,0x80008000,0x80008000,0x3f803f80,0x3f803f80,0x3f803f80,0x3f803f80,0x3f803f80,0x3f803f80,0x3f803f80,0x3f803f80,
0x3f803f80,0x3f803f80,0x3f803f80,0x3f803f80,0x3f803f80,0x3f803f80,0x3f803f80,0x3f803f80,0xbf7bbf80,0xbf55bf6d,0xbf0ebf35,0xbe48bec4,
0xbe488000,0xbf0ebec4,0xbf55bf35,0xbf7bbf6d,0x3f7b3f80,0x3f553f6d,0x3f0e3f35,0x3e483ec4,0x3e488000,0x3f0e3ec4,0x3f553f35,0x3f7b3f6d,
0xbe480000,0xbf0ebec4,0xbf55bf35,0xbf7bbf6d,0x3f7b3f80,0x3f553f6d,0x3f0e3f35,0x3e483ec4,0x3e480000,0x3f0e3ec4,0x3f553f35,0x3f7b3f6d,
0xbf7bbf80,0xbf55bf6d,0xbf0ebf35,0xbe48bec4,0xbec48000,0xbf6dbf35,0xbf6dbf80,0xbec4bf35,0x3ec48000,0x3f6d3f35,0x3f6d3f80,0x3ec43f35,
0xbec48000,0xbf6dbf35,0xbf6dbf80,0xbec4bf35,0x3ec48000,0x3f6d3f35,0x3f6d3f80,0x3ec43f35,0x3f6d3f80,0x3ec43f35,0xbec40000,0xbf6dbf35,
0xbf6dbf80,0xbec4bf35,0x3ec40000,0x3f6d3f35,0x3f6d3f80,0x3ec43f35,0xbec40000,0xbf6dbf35,0xbf6dbf80,0xbec4bf35,0x3ec40000,0x3f6d3f35,
0xbf55bf80,0x3e48bec4,0x3f7b3f35,0x3f0e3f6d,0x3f0e8000,0x3f7b3f6d,0x3e483f35,0xbf55bec4,0x3f553f80,0xbe483ec4,0xbf7bbf35,0xbf0ebf6d,
0xbf0e8000,0xbf7bbf6d,0xbe48bf35,0x3f553ec4,0xbf0e0000,0xbf7bbf6d,0xbe48bf35,0x3f553ec4,0xbf55bf80,0x3e48bec4,0x3f7b3f35,0x3f0e3f6d,
0x3f0e0000,0x3f7b3f6d,0x3e483f35,0xbf55bec4,0x3f553f80,0xbe483ec4,0xbf7bbf35,0xbf0ebf6d,0x3f353f80,0xbf350000,0xbf35bf80,0x3f350000,
0x3f353f80,0xbf350000,0xbf35bf80,0x3f350000,0x3f353f80,0xbf350000,0xbf35bf80,0x3f350000,0x3f353f80,0xbf350000,0xbf35bf80,0x3f350000,
0xbf358000,0xbf35bf80,0x3f358000,0x3f353f80,0xbf358000,0xbf35bf80,0x3f358000,0x3f353f80,0xbf358000,0xbf35bf80,0x3f358000,0x3f353f80,
0xbf358000,0xbf35bf80,0x3f358000,0x3f353f80,0xbf550000,0xbe48bf6d,0x3f7b3f35,0xbf0e3ec4,0x3f0e3f80,0xbf7bbec4,0x3e48bf35,0x3f553f6d,
0x3f550000,0x3e483f6d,0xbf7bbf35,0x3f0ebec4,0xbf0ebf80,0x3f7b3ec4,0xbe483f35,0xbf55bf6d,0xbf0ebf80,0x3f7b3ec4,0xbe483f35,0xbf55bf6d,
0xbf558000,0xbe48bf6d,0x3f7b3f35,0xbf0e3ec4,0x3f0e3f80,0xbf7bbec4,0x3e48bf35,0x3f553f6d,0x3f558000,0x3e483f6d,0xbf7bbf35,0x3f0ebec4,
0x3ec43f80,0xbf6dbf35,0x3f6d0000,0xbec43f35,0xbec4bf80,0x3f6d3f35,0xbf6d0000,0x3ec4bf35,0x3ec43f80,0xbf6dbf35,0x3f6d0000,0xbec43f35,
0xbec4bf80,0x3f6d3f35,0xbf6d0000,0x3ec4bf35,0xbf6d8000,0x3ec4bf35,0x3ec43f80,0xbf6dbf35,0x3f6d8000,0xbec43f35,0xbec4bf80,0x3f6d3f35,
0xbf6d8000,0x3ec4bf35,0x3ec43f80,0xbf6dbf35,0x3f6d8000,0xbec43f35,0xbec4bf80,0x3f6d3f35,0xbf7b0000,0x3f55bec4,0xbf0e3f35,0x3e48bf6d,
0xbe48bf80,0x3f0e3f6d,0xbf55bf35,0x3f7b3ec4,0x3f7b0000,0xbf553ec4,0x3f0ebf35,0xbe483f6d,0x3e483f80,0xbf0ebf6d,0x3f553f35,0xbf7bbec4,
0xbe48bf80,0x3f0e3f6d,0xbf55bf35,0x3f7b3ec4,0x3f7b8000,0xbf553ec4,0x3f0ebf35,0xbe483f6d,0x3e483f80,0xbf0ebf6d,0x3f553f35,0xbf7bbec4,
0xbf7b8000,0x3f55bec4,0xbf0e3f35,0x3e48bf6d,0xbf808000,0x3f808000,0xbf808000,0x3f808000,0xbf808000,0x3f808000,0xbf808000,0x3f808000,
0xbf808000,0x3f808000,0xbf808000,0x3f808000,0xbf808000,0x3f808000,0xbf808000,0x3f808000,0x3f80,0xbf80,0x3f80,0xbf80,
0x3f80,0xbf80,0x3f80,0xbf80,0x3f80,0xbf80,0x3f80,0xbf80,0x3f80,0xbf80,0x3f80,0xbf80,
0x3e48bf80,0xbf0e3f6d,0x3f55bf35,0xbf7b3ec4,0xbf7b8000,0x3f553ec4,0xbf0ebf35,0x3e483f6d,0xbe483f80,0x3f0ebf6d,0xbf553f35,0x3f7bbec4,
0x3f7b8000,0xbf55bec4,0x3f0e3f35,0xbe48bf6d,0xbf7b0000,0x3f553ec4,0xbf0ebf35,0x3e483f6d,0xbe483f80,0x3f0ebf6d,0xbf553f35,0x3f7bbec4,
0x3f7b0000,0xbf55bec4,0x3f0e3f35,0xbe48bf6d,0x3e48bf80,0xbf0e3f6d,0x3f55bf35,0xbf7b3ec4,0xbf6d8000,0x3ec43f35,0x3ec4bf80,0xbf6d3f35,
0x3f6d8000,0xbec4bf35,0xbec43f80,0x3f6dbf35,0xbf6d8000,0x3ec43f35,0x3ec4bf80,0xbf6d3f35,0x3f6d8000,0xbec4bf35,0xbec43f80,0x3f6dbf35,
0xbec43f80,0x3f6dbf35,0xbf6d0000,0x3ec43f35,0x3ec4bf80,0xbf6d3f35,0x3f6d0000,0xbec4bf35,0xbec43f80,0x3f6dbf35,0xbf6d0000,0x3ec43f35,
0x3ec4bf80,0xbf6d3f35,0x3f6d0000,0xbec4bf35,0x3f0ebf80,0xbf7b3ec4,0x3e483f35,0x3f55bf6d,0x3f558000,0x3e48bf6d,0xbf7b3f35,0x3f0e3ec4,
0xbf0e3f80,0x3f7bbec4,0xbe48bf35,0xbf553f6d,0xbf558000,0xbe483f6d,0x3f7bbf35,0xbf0ebec4,0xbf550000,0xbe483f6d,0x3f7bbf35,0xbf0ebec4,
0x3f0ebf80,0xbf7b3ec4,0x3e483f35,0x3f55bf6d,0x3f550000,0x3e48bf6d,0xbf7b3f35,0x3f0e3ec4,0xbf0e3f80,0x3f7bbec4,0xbe48bf35,0xbf553f6d,
0xbf353f80,0x3f350000,0x3f35bf80,0xbf350000,0xbf353f80,0x3f350000,0x3f35bf80,0xbf350000,0xbf353f80,0x3f350000,0x3f35bf80,0xbf350000,
0xbf353f80,0x3f350000,0x3f35bf80,0xbf350000,0xbf358000,0xbf353f80,0x3f358000,0x3f35bf80,0xbf358000,0xbf353f80,0x3f358000,0x3f35bf80,
0xbf358000,0xbf353f80,0x3f358000,0x3f35bf80,0xbf358000,0xbf353f80,0x3f358000,0x3f35bf80,0xbf0e0000,0xbf7b3f6d,0xbe483f35,0x3f55bec4,
0xbf553f80,0x3e483ec4,0x3f7bbf35,0x3f0ebf6d,0x3f0e0000,0x3f7bbf6d,0x3e48bf35,0xbf553ec4,0x3f55bf80,0xbe48bec4,0xbf7b3f35,0xbf0e3f6d,
0x3f55bf80,0xbe48bec4,0xbf7b3f35,0xbf0e3f6d,0xbf0e8000,0xbf7b3f6d,0xbe483f35,0x3f55bec4,0xbf553f80,0x3e483ec4,0x3f7bbf35,0x3f0ebf6d,
0x3f0e8000,0x3f7bbf6d,0x3e48bf35,0xbf553ec4,0xbf6d3f80,0xbec43f35,0x3ec40000,0x3f6dbf35,0x3f6dbf80,0x3ec4bf35,0xbec40000,0xbf6d3f35,
0xbf6d3f80,0xbec43f35,0x3ec40000,0x3f6dbf35,0x3f6dbf80,0x3ec4bf35,0xbec40000,0xbf6d3f35,0xbec48000,0xbf6d3f35,0xbf6d3f80,0xbec43f35,
0x3ec48000,0x3f6dbf35,0x3f6dbf80,0x3ec4bf35,0xbec48000,0xbf6d3f35,0xbf6d3f80,0xbec43f35,0x3ec48000,0x3f6dbf35,0x3f6dbf80,0x3ec4bf35,
0xbe480000,0xbf0e3ec4,0xbf553f35,0xbf7b3f6d,0x3f7bbf80,0x3f55bf6d,0x3f0ebf35,0x3e48bec4,0x3e480000,0x3f0ebec4,0x3f55bf35,0x3f7bbf6d,
0xbf7b3f80,0xbf553f6d,0xbf0e3f35,0xbe483ec4,0x3f7bbf80,0x3f55bf6d,0x3f0ebf35,0x3e48bec4,0x3e488000,0x3f0ebec4,0x3f55bf35,0x3f7bbf6d,
0xbf7b3f80,0xbf553f6d,0xbf0e3f35,0xbe483ec4,0xbe488000,0xbf0e3ec4,0xbf553f35,0xbf7b3f6d,0x80008000,0x80008000,0x80008000,0x80008000,
0x80008000,0x80008000,0x80008000,0x80008000,0x80008000,0x80008000,0x80008000,0x80008000,0x80008000,0x80008000,0x80008000,0x80008000,
0xbf803f80,0xbf803f80,0xbf803f80,0xbf803f80,0xbf803f80,0xbf803f80,0xbf803f80,0xbf803f80,0xbf803f80,0xbf803f80,0xbf803f80,0xbf803f80,
0xbf803f80,0xbf803f80,0xbf803f80,0xbf803f80,0x3f7bbf80,0x3f55bf6d,0x3f0ebf35,0x3e48bec4,0x3e488000,0x3f0ebec4,0x3f55bf35,0x3f7bbf6d,
0xbf7b3f80,0xbf553f6d,0xbf0e3f35,0xbe483ec4,0xbe488000,0xbf0e3ec4,0xbf553f35,0xbf7b3f6d,0x3e480000,0x3f0ebec4,0x3f55bf35,0x3f7bbf6d,
0xbf7b3f80,0xbf553f6d,0xbf0e3f35,0xbe483ec4,0xbe480000,0xbf0e3ec4,0xbf553f35,0xbf7b3f6d,0x3f7bbf80,0x3f55bf6d,0x3f0ebf35,0x3e48bec4,
0x3ec48000,0x3f6dbf35,0x3f6dbf80,0x3ec4bf35,0xbec48000,0xbf6d3f35,0xbf6d3f80,0xbec43f35,0x3ec48000,0x3f6dbf35,0x3f6dbf80,0x3ec4bf35,
0xbec48000,0xbf6d3f35,0xbf6d3f80,0xbec43f35,0xbf6d3f80,0xbec43f35,0x3ec40000,0x3f6dbf35,0x3f6dbf80,0x3ec4bf35,0xbec40000,0xbf6d3f35,
0xbf6d3f80,0xbec43f35,0x3ec40000,0x3f6dbf35,0x3f6dbf80,0x3ec4bf35,0xbec40000,0xbf6d3f35,0x3f55bf80,0xbe48bec4,0xbf7b3f35,0xbf0e3f6d,
0xbf0e8000,0xbf7b3f6d,0xbe483f35,0x3f55bec4,0xbf553f80,0x3e483ec4,0x3f7bbf35,0x3f0ebf6d,0x3f0e8000,0x3f7bbf6d,0x3e48bf35,0xbf553ec4,
0x3f0e0000,0x3f7bbf6d,0x3e48bf35,0xbf553ec4,0x3f55bf80,0xbe48bec4,0xbf7b3f35,0xbf0e3f6d,0xbf0e0000,0xbf7b3f6d,0xbe483f35,0x3f55bec4,
0xbf553f80,0x3e483ec4,0x3f7bbf35,0x3f0ebf6d,0xbf353f80,0x3f350000,0x3f35bf80,0xbf350000,0xbf353f80,0x3f350000,0x3f35bf80,0xbf350000,
0xbf353f80,0x3f350000,0x3f35bf80,0xbf350000,0xbf353f80,0x3f350000,0x3f35bf80,0xbf350000,0x3f358000,0x3f35bf80,0xbf358000,0xbf353f80,
0x3f358000,0x3f35bf80,0xbf358000,0xbf353f80,0x3f358000,0x3f35bf80,0xbf358000,0xbf353f80,0x3f358000,0x3f35bf80,0xbf358000,0xbf353f80,
0x3f550000,0x3e48bf6d,0xbf7b3f35,0x3f0e3ec4,0xbf0e3f80,0x3f7bbec4,0xbe48bf35,0xbf553f6d,0xbf550000,0xbe483f6d,0x3f7bbf35,0xbf0ebec4,
0x3f0ebf80,0xbf7b3ec4,0x3e483f35,0x3f55bf6d,0x3f0ebf80,0xbf7b3ec4,0x3e483f35,0x3f55bf6d,0x3f558000,0x3e48bf6d,0xbf7b3f35,0x3f0e3ec4,
0xbf0e3f80,0x3f7bbec4,0xbe48bf35,0xbf553f6d,0xbf558000,0xbe483f6d,0x3f7bbf35,0xbf0ebec4,0xbec43f80,0x3f6dbf35,0xbf6d0000,0x3ec43f35,
0x3ec4bf80,0xbf6d3f35,0x3f6d0000,0xbec4bf35,0xbec43f80,0x3f6dbf35,0xbf6d0000,0x3ec43f35,0x3ec4bf80,0xbf6d3f35,0x3f6d0000,0xbec4bf35,
0x3f6d8000,0xbec4bf35,0xbec43f80,0x3f6dbf35,0xbf6d8000,0x3ec43f35,0x3ec4bf80,0xbf6d3f35,0x3f6d8000,0xbec4bf35,0xbec43f80,0x3f6dbf35,
0xbf6d8000,0x3ec43f35,0x3ec4bf80,0xbf6d3f35,0x3f7b0000,0xbf55bec4,0x3f0e3f35,0xbe48bf6d,0x3e48bf80,0xbf0e3f6d,0x3f55bf35,0xbf7b3ec4,
0xbf7b0000,0x3f553ec4,0xbf0ebf35,0x3e483f6d,0xbe483f80,0x3f0ebf6d,0xbf553f35,0x3f7bbec4,0x3e48bf80,0xbf0e3f6d,0x3f55bf35,0xbf7b3ec4,
0xbf7b8000,0x3f553ec4,0xbf0ebf35,0x3e483f6d,0xbe483f80,0x3f0ebf6d,0xbf553f35,0x3f7bbec4,0x3f7b8000,0xbf55bec4,0x3f0e3f35,0xbe48bf6d,
0x3f808000,0xbf808000,0x3f808000,0xbf808000,0x3f808000,0xbf808000,0x3f808000,0xbf808000,0x3f808000,0xbf808000,0x3f808000,0xbf808000,
0x3f808000,0xbf808000,0x3f808000,0xbf808000,0x3f80,0xbf80,0x3f80,0xbf80,0x3f80,0xbf80,0x3f80,0xbf80,
0x3f80,0xbf80,0x3f80,0xbf80,0x3f80,0xbf80,0x3f80,0xbf80,0xbe48bf80,0x3f0e3f6d,0xbf55bf35,0x3f7b3ec4,
0x3f7b8000,0xbf553ec4,0x3f0ebf35,0xbe483f6d,0x3e483f80,0xbf0ebf6d,0x3f553f35,0xbf7bbec4,0xbf7b8000,0x3f55bec4,0xbf0e3f35,0x3e48bf6d,
0x3f7b0000,0xbf553ec4,0x3f0ebf35,0xbe483f6d,0x3e483f80,0xbf0ebf6d,0x3f553f35,0xbf7bbec4,0xbf7b0000,0x3f55bec4,0xbf0e3f35,0x3e48bf6d,
0xbe48bf80,0x3f0e3f6d,0xbf55bf35,0x3f7b3ec4,0x3f6d8000,0xbec43f35,0xbec4bf80,0x3f6d3f35,0xbf6d8000,0x3ec4bf35,0x3ec43f80,0xbf6dbf35,
0x3f6d8000,0xbec43f35,0xbec4bf80,0x3f6d3f35,0xbf6d8000,0x3ec4bf35,0x3ec43f80,0xbf6dbf35,0x3ec43f80,0xbf6dbf35,0x3f6d0000,0xbec43f35,
0xbec4bf80,0x3f6d3f35,0xbf6d0000,0x3ec4bf35,0x3ec43f80,0xbf6dbf35,0x3f6d0000,0xbec43f35,0xbec4bf80,0x3f6d3f35,0xbf6d0000,0x3ec4bf35,
0xbf0ebf80,0x3f7b3ec4,0xbe483f35,0xbf55bf6d,0xbf558000,0xbe48bf6d,0x3f7b3f35,0xbf0e3ec4,0x3f0e3f80,0xbf7bbec4,0x3e48bf35,0x3f553f6d,
0x3f558000,0x3e483f6d,0xbf7bbf35,0x3f0ebec4,0x3f550000,0x3e483f6d,0xbf7bbf35,0x3f0ebec4,0xbf0ebf80,0x3f7b3ec4,0xbe483f35,0xbf55bf6d,
0xbf550000,0xbe48bf6d,0x3f7b3f35,0xbf0e3ec4,0x3f0e3f80,0xbf7bbec4,0x3e48bf35,0x3f553f6d,0x3f353f80,0xbf350000,0xbf35bf80,0x3f350000,
0x3f353f80,0xbf350000,0xbf35bf80,0x3f350000,0x3f353f80,0xbf350000,0xbf35bf80,0x3f350000,0x3f353f80,0xbf350000,0xbf35bf80,0x3f350000,
0x3f358000,0x3f353f80,0xbf358000,0xbf35bf80,0x3f358000,0x3f353f80,0xbf358000,0xbf35bf80,0x3f358000,0x3f353f80,0xbf358000,0xbf35bf80,
0x3f358000,0x3f353f80,0xbf358000,0xbf35bf80,0x3f0e0000,0x3f7b3f6d,0x3e483f35,0xbf55bec4,0x3f553f80,0xbe483ec4,0xbf7bbf35,0xbf0ebf6d,
0xbf0e0000,0xbf7bbf6d,0xbe48bf35,0x3f553ec4,0xbf55bf80,0x3e48bec4,0x3f7b3f35,0x3f0e3f6d,0xbf55bf80,0x3e48bec4,0x3f7b3f35,0x3f0e3f6d,
0x3f0e8000,0x3f7b3f6d,0x3e483f35,0xbf55bec4,0x3f553f80,0xbe483ec4,0xbf7bbf35,0xbf0ebf6d,0xbf0e8000,0xbf7bbf6d,0xbe48bf35,0x3f553ec4,
0x3f6d3f80,0x3ec43f35,0xbec40000,0xbf6dbf35,0xbf6dbf80,0xbec4bf35,0x3ec40000,0x3f6d3f35,0x3f6d3f80,0x3ec43f35,0xbec40000,0xbf6dbf35,
0xbf6dbf80,0xbec4bf35,0x3ec40000,0x3f6d3f35,0x3ec48000,0x3f6d3f35,0x3f6d3f80,0x3ec43f35,0xbec48000,0xbf6dbf35,0xbf6dbf80,0xbec4bf35,
0x3ec48000,0x3f6d3f35,0x3f6d3f80,0x3ec43f35,0xbec48000,0xbf6dbf35,0xbf6dbf80,0xbec4bf35,0x3e480000,0x3f0e3ec4,0x3f553f35,0x3f7b3f6d,
0xbf7bbf80,0xbf55bf6d,0xbf0ebf35,0xbe48bec4,0xbe480000,0xbf0ebec4,0xbf55bf35,0xbf7bbf6d,0x3f7b3f80,0x3f553f6d,0x3f0e3f35,0x3e483ec4,
0xbf7bbf80,0xbf55bf6d,0xbf0ebf35,0xbe48bec4,0xbe488000,0xbf0ebec4,0xbf55bf35,0xbf7bbf6d,0x3f7b3f80,0x3f553f6d,0x3f0e3f35,0x3e483ec4,
0x3e488000,0x3f0e3ec4,0x3f553f35,0x3f7b3f6d,0x3f803f80,0x80008000,0x3f803f80,0x80008000,0x3f803f80,0x80008000,0x3f803f80,0x80008000,
0x3f803f80,0x80008000,0x3f803f80,0x80008000,0x3f803f80,0x80008000,0x3f803f80,0x80008000,0x3f803f80,0xbbc98000,0x3f803f80,0xbd62bd49,
0x3f803f80,0xbc97bc49,0x3f7f3f80,0xbd8abd7b,0x3f803f80,0xbcfbbcc9,0x3f7f3f7f,0xbda3bd97,0x3f803f80,0xbd30bd17,0x3f7f3f7f,0xbdbcbdb0,
0x3f803f80,0xbc498000,0x3f7e3f7f,0xbde2bdc9,0x3f803f80,0xbd17bcc9,0x3f7e3f7e,0xbe0abdfb,0x3f803f80,0xbd7bbd49,0x3f7d3f7d,0xbe23be16,
0x3f7f3f7f,0xbdb0bd97,0x3f7c3f7c,0xbe3bbe2f,0x3f803f80,0xbc978000,0x3f7c3f7d,0xbe29be16,0x3f803f80,0xbd62bd17,0x3f7b3f7c,0xbe4ebe3b,
0x3f7f3f7f,0xbdbcbd97,0x3f793f7a,0xbe73be60,0x3f7e3f7e,0xbe04bde2,0x3f763f78,0xbe8cbe82,0x3f803f80,0xbcc98000,0x3f7a3f7b,0xbe60be48,
0x3f7f3f80,0xbd97bd49,0x3f773f78,0xbe89be79,0x3f7e3f7f,0xbdfbbdc9,0x3f733f75,0xbea1be95,0x3f7c3f7d,0xbe2fbe16,0x3f6f3f71,0xbeb8beac,
0x3f803f80,0xbcfb8000,0x3f763f78,0xbe8cbe79,0x3f7f3f80,0xbdbcbd7b,0x3f723f74,0xbeaabe9b,0x3f7d3f7e,0xbe1cbdfb,0x3f6c3f6f,0xbec7beb8,
0x3f7a3f7c,0xbe5abe3b,0x3f653f69,0xbee3bed5,0x3f803f80,0xbd178000,0x3f723f75,0xbea7be95,0x3f7e3f7f,0xbde2bd97,0x3f6b3f6f,0xbecabeb8,
0x3f7c3f7d,0xbe3bbe16,0x3f633f67,0xbeecbedb,0x3f783f7a,0xbe82be60,0x3f5a3f5f,0xbf06befc,0x3f803f80,0xbd308000,0x3f6d3f71,0xbec1beac,
0x3f7e3f7f,0xbe04bdb0,0x3f643f69,0xbee9bed5,0x3f7a3f7c,0xbe5abe2f,0x3f593f5f,0xbf08befc,0x3f753f78,0xbe98be82,0x3f4d3f53,0xbf1abf11,
0x3f803f80,0x80008000,0x3f803f80,0x80008000,0x3f803f80,0x80008000,0x3f803f80,0x80008000,0x3f803f80,0x80008000,0x3f803f80,0x80008000,
0x3f803f80,0x80008000,0x3f803f80,0x80008000,0x3f7f3f7f,0xbdd5bdc9,0x3f7d3f7d,0xbe1cbe16,0x3f7e3f7e,0xbdeebde2,0x3f7c3f7d,0xbe29be23,
0x3f7e3f7e,0xbe04bdfb,0x3f7c3f7c,0xbe35be2f,0x3f7d3f7e,0xbe10be0a,0x3f7b3f7c,0xbe42be3b,0x3f7a3f7b,0xbe54be48,0x3f743f75,0xbe9bbe95,
0x3f793f7a,0xbe6dbe60,0x3f723f73,0xbea7bea1,0x3f783f78,0xbe82be79,0x3f703f71,0xbeb2beac,0x3f763f77,0xbe8fbe89,0x3f6e3f6f,0xbebebeb8,
0x3f743f75,0xbe9ebe95,0x3f653f67,0xbee3bedb,0x3f713f72,0xbeafbea7,0x3f613f63,0xbef4beec,0x3f6d3f6f,0xbec1beb8,0x3f5c3f5f,0xbf02befc,
0x3f693f6b,0xbed2beca,0x3f573f5a,0xbf0abf06,0x3f6a3f6d,0xbecfbec4,0x3f513f55,0xbf13bf0e,0x3f653f67,0xbee6bedb,0x3f4a3f4e,0xbf1dbf18,
0x3f5f3f62,0xbefcbef1,0x3f423f46,0xbf27bf22,0x3f583f5c,0xbf09bf04,0x3f393f3e,0xbf31bf2c,0x3f5e3f62,0xbeffbef1,0x3f383f3e,0xbf32bf2c,
0x3f563f5a,0xbf0dbf06,0x3f2d3f33,0xbf3dbf37,0x3f4d3f51,0xbf1abf13,0x3f213f27,0xbf47bf42,0x3f433f48,0xbf26bf20,0x3f153f1b,0xbf50bf4c,
0x3f4f3f55,0xbf16bf0e,0x3f1b3f22,0xbf4cbf46,0x3f443f4a,0xbf25bf1d,0x3f0c3f13,0xbf57bf51,0x3f373f3e,0xbf33bf2c,0x3ef73f04,0xbf60bf5c,
0x3f2a3f31,0xbf40bf39,0x3ed53ee6,0xbf69bf65,0x3f3f3f46,0xbf2bbf22,0x3ef43f04,0xbf61bf5c,0x3f2f3f37,0xbf3abf33,0x3ecd3ee1,0xbf6bbf66,
0x3f1f3f27,0xbf49bf42,0x3ea43eb8,0xbf73bf6f,0x3f0d3f16,0xbf56bf4f,0x3e733e8f,0xbf79bf76,0x3f803f80,0xbd498000,0x3f673f6d,0xbedbbec4,
0x3f7d3f7f,0xbe16bdc9,0x3f5c3f62,0xbf04bef1,0x3f783f7b,0xbe79be48,0x3f4e3f55,0xbf18bf0e,0x3f713f75,0xbeacbe95,0x3f3e3f46,0xbf2cbf22,
0x3f803f80,0xbd628000,0x3f613f67,0xbef4bedb,0x3f7c3f7e,0xbe29bde2,0x3f523f5a,0xbf12bf06,0x3f763f7a,0xbe8cbe60,0x3f413f4a,0xbf28bf1d,
0x3f6d3f72,0xbec1bea7,0x3f2d3f37,0xbf3dbf33,0x3f803f80,0xbd7b8000,0x3f5a3f62,0xbf06bef1,0x3f7c3f7e,0xbe3bbdfb,0x3f483f51,0xbf20bf13,
0x3f743f78,0xbe9bbe79,0x3f333f3e,0xbf37bf2c,0x3f693f6f,0xbed5beb8,0x3f1b3f27,0xbf4cbf42,0x3f7f3f80,0xbd8a8000,0x3f523f5c,0xbf12bf04,
0x3f7b3f7e,0xbe4ebe0a,0x3f3d3f48,0xbf2dbf20,0x3f723f77,0xbeaabe89,0x3f243f31,0xbf45bf39,0x3f643f6b,0xbee9beca,0x3f083f16,0xbf59bf4f,
0x3f7f3f80,0xbd978000,0x3f4a3f55,0xbf1dbf0e,0x3f7a3f7d,0xbe60be16,0x3f313f3e,0xbf39bf2c,0x3f6f3f75,0xbeb8be95,0x3f133f22,0xbf51bf46,
0x3f5f3f67,0xbefcbedb,0x3ee63f04,0xbf65bf5c,0x3f7f3f80,0xbda38000,0x3f413f4e,0xbf28bf18,0x3f793f7d,0xbe73be23,0x3f243f33,0xbf45bf37,
0x3f6c3f73,0xbec7bea1,0x3f023f13,0xbf5cbf51,0x3f593f63,0xbf08beec,0x3ebb3ee1,0xbf6ebf66,0x3f7f3f80,0xbdb08000,0x3f373f46,0xbf33bf22,
0x3f783f7c,0xbe82be2f,0x3f163f27,0xbf4fbf42,0x3f693f71,0xbed5beac,0x3ee13f04,0xbf66bf5c,0x3f533f5f,0xbf11befc,0x3e8f3eb8,0xbf76bf6f,
0x3f7f3f80,0xbdbc8000,0x3f2d3f3e,0xbf3dbf2c,0x3f763f7c,0xbe8cbe3b,0x3f083f1b,0xbf59bf4c,0x3f653f6f,0xbee3beb8,0x3ebb3ee6,0xbf6ebf65,
0x3f4d3f5a,0xbf1abf06,0x3e423e8f,0xbf7bbf76,0x3f2c3f35,0xbf3ebf35,0x3eac3ec4,0xbf71bf6d,0x3f183f22,0xbf4ebf46,0x3e793e95,0xbf78bf75,
0x3f043f0e,0xbf5cbf55,0x3e163e48,0xbf7dbf7b,0x3edb3ef1,0xbf67bf62,0x3d493dc9,0xbf80bf7f,0x3f173f22,0xbf4fbf46,0x3e423e79,0xbf7bbf78,
0x3eff3f0c,0xbf5ebf57,0x3da33e0a,0xbf7fbf7e,0x3ecd3ee6,0xbf6bbf65,0xbcfb3cc9,0xbf80bf80,0x3e983eb2,0xbf75bf70,0xbe10bdb0,0xbf7dbf7f,
0x3f013f0e,0xbf5dbf55,0x3d173dc9,0xbf80bf7f,0x3eca3ee6,0xbf6bbf65,0xbdb0bcc9,0xbf7fbf80,0x3e8f3eac,0xbf76bf71,0xbe54be16,0xbf7abf7d,
0x3e233e60,0xbf7dbf7a,0xbea7be89,0xbf72bf77,0x3ed23ef1,0xbf69bf62,0xbdeebd49,0xbf7ebf80,0x3e923eb2,0xbf75bf70,0xbe7fbe3b,0xbf78bf7c,
0x3e1c3e60,0xbf7dbf7a,0xbec1bea1,0xbf6dbf73,0x3c973db0,0xbf80bf7f,0xbeffbee1,0xbf5ebf66,0x3ea13ec4,0xbf73bf6d,0xbe89be48,0xbf77bf7b,
0x3e2f3e79,0xbf7cbf78,0xbecfbeac,0xbf6abf71,0x3cc93dc9,0xbf80bf7f,0xbf09bef1,0xbf58bf62,0xbdfbbd49,0xbf7ebf80,0xbf27bf18,0xbf42bf4e,
0x3e5a3e95,0xbf7abf75,0xbed2beac,0xbf69bf71,0x3d623e0a,0xbf80bf7e,0xbf0dbef7,0xbf56bf60,0xbdd5bcc9,0xbf7fbf80,0xbf2dbf1d,0xbf3dbf4a,
0xbe86be3b,0xbf77bf7c,0xbf49bf3c,0xbf1fbf2e,0x3de23e48,0xbf7ebf7b,0xbf0cbef1,0xbf57bf62,0xbd7b3cc9,0xbf80bf80,0xbf2ebf1d,0xbf3cbf4a,
0xbe6dbe16,0xbf79bf7d,0xbf4cbf3e,0xbf1bbf2c,0xbecabea1,0xbf6bbf73,0xbf63bf58,0xbeecbf09,0x3bc93dc9,0xbf80bf7f,0xbf2bbf18,0xbf3fbf4e,
0xbe35bdb0,0xbf7cbf7f,0xbf4bbf3c,0xbf1cbf2e,0xbeb5be89,0xbf6fbf77,0xbf64bf58,0xbee9bf09,0xbf05bee1,0xbf5bbf66,0xbf75bf6e,0xbe92bebe,
0x3f7f3f80,0xbdc98000,0x3f223f35,0xbf46bf35,0x3f753f7b,0xbe95be48,0x3ef13f0e,0xbf62bf55,0x3f623f6d,0xbef1bec4,0x3e953ec4,0xbf75bf6d,
0x3f463f55,0xbf22bf0e,0x3dc93e48,0xbf7fbf7b,0x3f7f3f80,0xbdd58000,0x3f173f2c,0xbf4fbf3e,0x3f743f7a,0xbe9ebe54,0x3ed23f01,0xbf69bf5d,
0x3f5e3f6a,0xbeffbecf,0x3e5a3ea1,0xbf7abf73,0x3f3f3f4f,0xbf2bbf16,0x3bc93de2,0xbf80bf7e,0x3f7e3f80,0xbde28000,0x3f0c3f22,0xbf57bf46,
0x3f723f7a,0xbea7be60,0x3eb23ee6,0xbf70bf65,0x3f5a3f67,0xbf06bedb,0x3e0a3e79,0xbf7ebf78,0x3f373f4a,0xbf33bf1d,0xbdb03cc9,0xbf7fbf80,
0x3f7e3f80,0xbdee8000,0x3eff3f18,0xbf5ebf4e,0x3f713f79,0xbeafbe6d,0x3e923eca,0xbf75bf6b,0x3f563f65,0xbf0dbee6,0x3d623e2f,0xbf80bf7c,
0x3f2f3f44,0xbf3abf25,0xbe35bd7b,0xbf7cbf80,0x3f7e3f80,0xbdfb8000,0x3ee63f0e,0xbf65bf55,0x3f6f3f78,0xbeb8be79,0x3e603eac,0xbf7abf71,
0x3f513f62,0xbf13bef1,0xbcc93dc9,0xbf80bf7f,0x3f273f3e,0xbf42bf2c,0xbe89be16,0xbf77bf7d,0x3f7e3f80,0xbe048000,0x3ecd3f04,0xbf6bbf5c,
0x3f6d3f78,0xbec1be82,0x3e1c3e8f,0xbf7dbf76,0x3f4d3f5f,0xbf1abefc,0xbdd53cc9,0xbf7fbf80,0x3f1f3f37,0xbf49bf33,0xbeb5be6d,0xbf6fbf79,
0x3f7e3f80,0xbe0a8000,0x3eb23ef1,0xbf70bf62,0x3f6b3f77,0xbecabe89,0x3db03e60,0xbf7fbf7a,0x3f483f5c,0xbf20bf04,0xbe3bbd49,0xbf7cbf80,
0x3f163f31,0xbf4fbf39,0xbee1bea1,0xbf66bf73,0x3f7d3f80,0xbe108000,0x3e983edb,0xbf75bf67,0x3f693f76,0xbed2be8f,0x3c973e23,0xbf80bf7d,
0x3f433f58,0xbf26bf09,0xbe86bdfb,0xbf77bf7e,0x3f0d3f2a,0xbf56bf40,0xbf05beca,0xbf5bbf6b,0xbdc90000,0xbf7fbf80,0xbf46bf35,0xbf22bf35,
0xbe95be48,0xbf75bf7b,0xbf62bf55,0xbef1bf0e,0xbef1bec4,0xbf62bf6d,0xbf75bf6d,0xbe95bec4,0xbf22bf0e,0xbf46bf55,0xbf7fbf7b,0xbdc9be48,
0xbe4ebdc9,0xbf7bbf7f,0xbf5cbf4e,0xbf02bf18,0xbecdbe9b,0xbf6bbf74,0xbf73bf69,0xbea4bed5,0xbf15befc,0xbf50bf5f,0xbf7ebf7a,0xbdeebe60,
0xbf3dbf2a,0xbf2dbf40,0xbf7fbf80,0x3dbcbc49,0xbe9bbe48,0xbf74bf7b,0xbf6ebf62,0xbebebef1,0xbf01becf,0xbf5dbf6a,0xbf7dbf77,0xbe23be89,
0xbf2ebf18,0xbf3cbf4e,0xbf80bf80,0x3d7bbd49,0xbf53bf42,0xbf11bf27,0xbf76bf7c,0x3e8f3e2f,0xbecdbe95,0xbf6bbf75,0xbf79bf71,0xbe66beac,
0xbf1abf01,0xbf4dbf5d,0xbf80bf7e,0x3bc9bde2,0xbf45bf31,0xbf24bf39,0xbf79bf7e,0x3e733dfb,0xbf65bf57,0xbee3bf0c,0xbf64bf70,0x3ee93eb2,
0xbefcbec4,0xbf5fbf6d,0xbf7fbf7b,0xbd97be48,0xbf31bf18,0xbf39bf4e,0xbf7cbf80,0x3e2f3d49,0xbf58bf46,0xbf09bf22,0xbf6abf75,0x3ecf3e95,
0xbf73bf67,0xbea1bedb,0xbf4abf5c,0x3f1d3f04,0xbf15bef1,0xbf50bf62,0xbf7fbf80,0x3da3bd49,0xbf45bf2e,0xbf24bf3c,0xbf72bf7a,0x3eaa3e54,
0xbf68bf58,0xbed8bf09,0xbf54bf65,0x3f103ee6,0xbf7cbf74,0xbe35be9b,0xbf28bf40,0x3f413f2a,0xbf2abf0e,0xbf40bf55,0xbf79bf7f,0x3e6d3dc9,
0xbf57bf42,0xbf0cbf27,0xbf60bf6f,0x3ef73eb8,0xbf74bf67,0xbe9bbedb,0xbf37bf4e,0x3f333f18,0xbf80bf7c,0xbd17be2f,0xbf01bf1d,0x3f5d3f4a,
0xbf3dbf22,0xbf2dbf46,0xbf6dbf78,0x3ec13e79,0xbf65bf53,0xbee3bf11,0xbf49bf5d,0x3f1f3f01,0xbf7cbf73,0xbe35bea1,0xbf15bf31,0x3f503f39,
0xbf7fbf80,0x3dd5bd17,0xbeaabeec,0x3f723f63,0x3f7d3f80,0xbe168000,0x3e793ec4,0xbf78bf6d,0x3f673f75,0xbedbbe95,0xbd493dc9,0xbf80bf7f,
0x3f3e3f55,0xbf2cbf0e,0xbeacbe48,0xbf71bf7b,0x3f043f22,0xbf5cbf46,0xbf18bef1,0xbf4ebf62,0x3f7d3f80,0xbe1c8000,0x3e423eac,0xbf7bbf71,
0x3f653f74,0xbee3be9b,0xbdee3d17,0xbf7ebf80,0x3f383f51,0xbf32bf13,0xbed2be89,0xbf69bf77,0x3ef43f1b,0xbf61bf4c,0xbf2bbf0c,0xbf3fbf57,
0x3f7d3f80,0xbe238000,0x3e0a3e95,0xbf7ebf75,0x3f633f73,0xbeecbea1,0xbe3bbcc9,0xbf7cbf80,0x3f333f4e,0xbf37bf18,0xbef7beac,0xbf60bf71,
0x3ee13f13,0xbf66bf51,0xbf3cbf1d,0xbf2ebf4a,0x3f7c3f80,0xbe298000,0x3da33e79,0xbf7fbf78,0x3f613f72,0xbef4bea7,0xbe7fbdb0,0xbf78bf7f,
0x3f2d3f4a,0xbf3dbf1d,0xbf0dbecf,0xbf56bf6a,0x3ecd3f0c,0xbf6bbf57,0xbf4bbf2e,0xbf1cbf3c,0x3f7c3f80,0xbe2f8000,0x3cc93e48,0xbf80bf7b,
0x3f5f3f71,0xbefcbeac,0xbea1be16,0xbf73bf7d,0x3f273f46,0xbf42bf22,0xbf1dbef1,0xbf4abf62,0x3eb83f04,0xbf6fbf5c,0xbf58bf3e,0xbf09bf2c,
0x3f7c3f80,0xbe358000,0xbcfb3e16,0xbf80bf7d,0x3f5c3f70,0xbf02beb2,0xbec1be54,0xbf6dbf7a,0x3f213f42,0xbf47bf27,0xbf2dbf09,0xbf3dbf58,
0x3ea43ef7,0xbf73bf60,0xbf64bf4c,0xbee9bf1b,0x3f7c3f80,0xbe3b8000,0xbdb03dc9,0xbf7fbf7f,0x3f5a3f6f,0xbf06beb8,0xbee1be89,0xbf66bf77,
0x3f1b3f3e,0xbf4cbf2c,0xbf3cbf18,0xbf2ebf4e,0x3e8f3ee6,0xbf76bf65,0xbf6ebf58,0xbebebf09,0x3f7b3f80,0xbe428000,0xbe103d49,0xbf7dbf80,
0x3f573f6e,0xbf0abebe,0xbeffbea7,0xbf5ebf72,0x3f153f39,0xbf50bf31,0xbf49bf27,0xbf1fbf42,0x3e733ed5,0xbf79bf69,0xbf75bf63,0xbe92beec,
0xbf4ebf35,0xbf18bf35,0xbf5cbf6d,0x3f043ec4,0xbf71bf62,0xbeacbef1,0xbf2cbf46,0x3f3e3f22,0xbf80bf7b,0xbd49be48,0xbedbbf0e,0x3f673f55,
0xbf78bf7f,0x3e793dc9,0xbe16be95,0x3f7d3f75,0xbf5cbf46,0xbf02bf22,0xbf45bf5c,0x3f243f04,0xbf79bf6e,0xbe66bebe,0xbf0abf2a,0x3f573f40,
0xbf7fbf7f,0x3da3bd97,0xbe86becf,0x3f773f6a,0xbf6dbf79,0x3ec13e6d,0x3d30bde2,0x3f803f7e,0xbf69bf55,0xbed5bf0e,0xbf2abf46,0x3f403f22,
0xbf7ebf77,0xbde2be89,0xbecabf09,0x3f6b3f58,0xbf7abf80,0x3e543d49,0xbdb0be79,0x3f7f3f78,0xbf5dbf6f,0x3f013eb8,0x3e6d3d97,0x3f793f7f,
0xbf73bf62,0xbea4bef1,0xbf0abf2c,0x3f573f3e,0xbf80bf7d,0x3bc9be23,0xbe73beca,0x3f793f6b,0xbf72bf7c,0x3eaa3e2f,0x3dbcbd97,0x3f7f3f7f,
0xbf49bf60,0x3f1f3ef7,0x3ed23e82,0x3f693f78,0xbf7abf6d,0xbe60bec4,0xbecfbf0e,0x3f6a3f55,0xbf7ebf80,0x3dfbbd49,0xbd97be79,0x3f7f3f78,
0xbf65bf75,0x3ee63e95,0x3e893dc9,0x3f773f7f,0xbf31bf4e,0x3f393f18,0x3f133edb,0x3f513f67,0xbf7ebf75,0xbdeebe95,0xbe86bedb,0x3f773f67,
0xbf79bf80,0x3e733d7b,0x3dbcbdb0,0x3f7f3f7f,0xbf54bf6a,0x3f103ecf,0x3ede3e89,0x3f673f77,0xbf15bf37,0x3f503f33,0x3f383f16,0x3f323f4f,
0xbf80bf7b,0xbc49be48,0xbde2be95,0x3f7e3f75,0xbf70bf7c,0x3eb23e2f,0x3e823d97,0x3f783f7f,0xbf40bf5c,0x3f2a3f04,0x3f163edb,0x3f4f3f67,
0xbeecbf1d,0x3f633f4a,0x3f573f39,0x3f0c3f31,0xbf7fbf7f,0x3dbcbdc9,0x3d30be16,0x3f803f7d,0xbf64bf76,0x3ee93e8f,0x3ed23e6d,0x3f693f79,
0xbf28bf4a,0x3f413f1d,0x3f383f13,0x3f323f51,0xbeaabf01,0x3f723f5d,0x3f6d3f57,0x3ec13f0c,
};
__device__ const __align__(128) uint64_t c_inv[16384] = {
0x3f003f003f003f00,0x3f003f003f003f00,0x3f003f003f003f00,0x3f003f003f003f00,0x3f003f003f003f00,0x3f003f003f003f00,0x3f003f003f003f00,0x3f003f003f003f00,
0xbf00bf003f003f00,0xbf00bf003f003f00,0xbf00bf003f003f00,0xbf00bf003f003f00,0xbf00bf003f003f00,0xbf00bf003f003f00,0xbf00bf003f003f00,0xbf00bf003f003f00,
0x3f733f7a3f753f7b,0x3f6f3f773f713f78,0x3f7e3f803f7f3f80,0x3f7c3f7f3f7d3f80,0x3f423f513f463f55,0x3f393f4a3f3e3f4e,0x3f5f3f6a3f623f6d,0x3f583f653f5c3f67,
0xbea1be60be95be48,0xbeb8be89beacbe79,0xbdfbbcc9bdc98000,0xbe2fbd97be16bd49,0xbf27bf13bf22bf0e,0xbf31bf1dbf2cbf18,0xbefcbecfbef1bec4,0xbf09bee6bf04bedb,
0x3f043f2c3f0e3f35,0x3edb3f183ef13f22,0x3e163eac3e483ec4,0x3d493e793dc93e95,0x3f783f803f7b3f80,0x3f713f7d3f753f7f,0x3f4e3f673f553f6d,0x3f3e3f5c3f463f62,
0xbf5cbf3ebf55bf35,0xbf67bf4ebf62bf46,0xbf7dbf71bf7bbf6d,0xbf80bf78bf7fbf75,0xbe79bd49be488000,0xbeacbe16be95bdc9,0xbf18bedbbf0ebec4,0xbf2cbf04bf22bef1,
0xbf09be89bef1be48,0xbf27becfbf18beac,0x3cc93ea13dc93ec4,0xbdfb3e2fbd493e79,0x3f133f4a3f223f55,0x3ee63f313f043f3e,0x3f6f3f7f3f753f80,0x3f5f3f7a3f673f7d,
0xbf58bf77bf62bf7b,0xbf42bf6abf4ebf71,0xbf80bf73bf7fbf6d,0xbf7ebf7cbf80bf78,0xbf51bf1dbf46bf0e,0xbf65bf39bf5cbf2c,0xbeb8bd97be958000,0xbefcbe60bedbbe16,
0x3f623f7f3f6d3f80,0x3f463f753f553f7b,0x3e953f223ec43f35,0x3dc93ef13e483f0e,0xbef1bdc9bec40000,0xbf22be95bf0ebe48,0xbf75bf46bf6dbf35,0xbf7fbf62bf7bbf55,
0xbef1bdc9bec48000,0xbf22be95bf0ebe48,0xbf75bf46bf6dbf35,0xbf7fbf62bf7bbf55,0xbf62bf7fbf6dbf80,0xbf46bf75bf55bf7b,0xbe95bf22bec4bf35,0xbdc9bef1be48bf0e,
0xbcc93ee63dc93f0e,0xbe893e60be163eac,0x3f513f7e3f623f80,0x3f273f6f3f3e3f78,0xbf6abf7fbf75bf7b,0xbf4abf7cbf5cbf80,0xbf58befcbf46bec4,0xbf73bf31bf67bf18,
0xbf80bf65bf7fbf55,0xbf77bf7abf7dbf71,0xbf13bdfbbef18000,0xbf42beb8bf2cbe79,0x3ecfbd973e95be48,0x3f1d3e2f3f043d49,0xbf09bf5fbf22bf6d,0xbea1bf39bedbbf4e,
0xbf80bf4ebf7bbf35,0xbf78bf71bf7fbf62,0xbedbbf5cbf0ebf6d,0xbe16bf2cbe95bf46,0x3f3e3f7d3f553f80,0x3f043f673f223f75,0xbeac3e79be483ec4,0xbf18bd49bef13dc9,
0xbd49bf18be48bf35,0x3e79beac3dc9bef1,0x3f673f043f553ec4,0x3f7d3f3e3f753f22,0xbf2cbe16bf0e8000,0xbf5cbedbbf46be95,0xbf71bf78bf7bbf6d,0xbf4ebf80bf62bf7f,
0x3e89becf3dc9bf0e,0x3f13bd973edbbe79,0xbf65bf7abf75bf6d,0xbf31bf7ebf4ebf80,0xbf1d3cc9bef13e48,0xbf58bea1bf3ebe16,0x3f273f7c3f463f80,0x3eb83f5f3f043f71,
0x3f773f6a3f7f3f55,0x3f513f7f3f673f78,0x3ee6be603e95bec4,0x3f393dfb3f18bd49,0xbf4abf80bf62bf7b,0xbf09bf73bf2cbf7d,0xbf42be2fbf228000,0xbf6fbefcbf5cbeac,
0x3f0e3f7b3f353f80,0x3e483f553ec43f6d,0xbf55be48bf350000,0xbf7bbf0ebf6dbec4,0xbf0ebf7bbf35bf80,0xbe48bf55bec4bf6d,0x3f553e483f350000,0x3f7b3f0e3f6d3ec4,
0xbf55be48bf358000,0xbf7bbf0ebf6dbec4,0xbf0ebf7bbf35bf80,0xbe48bf55bec4bf6d,0x3f553e483f358000,0x3f7b3f0e3f6d3ec4,0x3f0e3f7b3f353f80,0x3e483f553ec43f6d,
0xbf77becfbf62be48,0xbf7cbf42bf80bf18,0x3ee63f7a3f223f80,0x3cc93f4a3e793f67,0x3f7e3f393f7f3f0e,0x3f583f733f713f5c,0xbd97bf51be95bf6d,0x3eb8befc3e16bf2c,
0xbe89bf6abef1bf7b,0x3e2fbf27bd49bf4e,0xbf65be60bf468000,0xbf80bf1dbf78bedb,0xbdfb3f313dc93f55,0xbf093ea1beac3f04,0x3f7f3f133f753ec4,0x3f6f3f5f3f7d3f3e,
0x3edbbf043e48bf35,0x3f4ebd493f22be95,0x3f2c3f7d3f553f6d,0x3e793f713ef13f7f,0x3eac3f783f0e3f80,0xbe163f3e3dc93f62,0xbf80bf18bf7bbec4,0xbf5cbf67bf75bf46,
0x3f673f5c3f7b3f35,0x3f183f803f463f75,0xbf3e3e16bf0e3ec4,0xbf78beacbf62bdc9,0xbf71be79bf558000,0xbf7dbf2cbf7fbef1,0x3d49bf4ebe48bf6d,0x3f04bedb3e95bf22,
0x3cc93f653e953f7b,0xbefc3f09be793f3e,0x3f51bdfb3f22bec4,0x3f7f3ecf3f713e16,0xbf6fbf42bf7fbf0e,0xbf1dbf7cbf4ebf67,0x3e603f773ef13f80,0xbea13f31bd493f5c,
0xbf80bee6bf75be48,0xbf5fbf58bf78bf2c,0x3f133f7e3f463f6d,0x3d973f6a3eac3f7d,0x3eb8bf273dc9bf55,0x3f4abe2f3f18bedb,0xbf7abe89bf628000,0xbf73bf39bf80bf04,
0x3dc93f753ec43f80,0xbef13f22be483f55,0xbf46bf62bf6dbf35,0xbe95bf7fbf0ebf7b,0x3f7f3e953f6d0000,0x3f623f463f7b3f0e,0xbf223ef1bec43f35,0xbf75bdc9bf553e48,
0xbf7fbe95bf6d8000,0xbf62bf46bf7bbf0e,0x3f22bef13ec4bf35,0x3f753dc93f55be48,0x3dc93f753ec43f80,0xbef13f22be483f55,0xbf46bf62bf6dbf35,0xbe95bf7fbf0ebf7b,
0xbf09bf77bf46bf55,0x3d97bf6fbe79bf80,0xbcc93f733e953f80,0xbf1d3f13beac3f4e,0xbf7cbdfbbf623e48,0xbf65bf31bf7dbedb,0x3f6a3f273f7f3ec4,0x3efc3f7a3f3e3f5c,
0x3f58be893f22bf0e,0x3f7f3eb83f783d49,0xbf80bea1bf758000,0xbf4abf51bf71bf18,0xbe2fbf7ebef1bf7b,0x3ee6bf393e16bf67,0xbecf3f42bdc93f6d,0xbf5f3e60bf2c3f04,
0x3f183f673f553f35,0xbd493f783e953f7f,0xbf5cbf2cbf7bbec4,0xbeacbf7dbf22bf62,0xbe163f713e483f80,0xbf3e3f04bef13f46,0xbe79bf80bf0ebf6d,0x3edbbf4e3dc9bf75,
0xbf4e3edbbf0e3f35,0xbf80be79bf753dc9,0x3f04bf3e3e48bf6d,0x3f71be163f46bef1,0xbf7dbeacbf7b8000,0xbf2cbf5cbf62bf22,0x3f78bd493f55bec4,0x3f673f183f7f3e95,
0xbea1bf7abf22bf55,0x3ecfbf5f3d49bf7d,0x3dfb3f803ef13f6d,0xbf133f42be793f71,0x3d97bf7cbe95bf7b,0x3f39bf1d3edbbf5c,0xbe893f6f3dc93f80,0xbf583ee6bf183f3e,
0x3f73be603f46bf0e,0x3f6a3efc3f803e16,0xbf7e3cc9bf623ec4,0xbf51bf27bf78beac,0x3f7f3e2f3f75be48,0x3f313f4a3f673f04,0xbf77beb8bf7f8000,0xbf09bf65bf4ebf2c,
0xbec43f6d00003f80,0xbf6d3ec4bf353f35,0x3ec4bf6d0000bf80,0x3f6dbec43f35bf35,0xbec43f6d00003f80,0xbf6d3ec4bf353f35,0x3ec4bf6d0000bf80,0x3f6dbec43f35bf35,
0xbf6dbec4bf808000,0xbec4bf6dbf35bf35,0x3f6d3ec43f808000,0x3ec43f6d3f353f35,0xbf6dbec4bf808000,0xbec4bf6dbf35bf35,0x3f6d3ec43f808000,0x3ec43f6d3f353f35,
0x3f27bf513e95bf7b,0x3f80bdfb3f67bf04,0xbefc3f6abdc93f80,0xbf7a3ea1bf4e3f2c,0x3f65bf093f22bf55,0x3f6f3e893f80be16,0xbf4a3f31bef13f6d,0xbf7cbd97bf783eac,
0x3f423f133f753e48,0x3cc93f7e3edb3f5c,0xbf5fbecfbf7f8000,0xbe60bf73bf18bf3e,0x3ee63f583f463f0e,0xbeb83f773d493f7d,0xbf1dbf39bf62bec4,0x3e2fbf7fbe79bf71,
0xbf7d3eacbf553f35,0xbf3ebf04bf75bdc9,0x3f783d493f7bbec4,0x3edb3f4e3f463ef1,0xbf183f67be483f80,0xbf803e79bf623f22,0x3f5cbf2c3f0ebf6d,0x3f713e163f7fbe95,
0xbe16bf71bf0ebf35,0x3f2cbf5c3e95bf7f,0xbe793f803e483f6d,0xbf673f18bf223f62,0xbf4ebedbbf7b8000,0xbd49bf78bef1bf46,0x3f043f3e3f553ec4,0xbeac3f7d3dc93f75,
0x3f133f1d3f623e48,0xbea13f803e163f67,0xbf6fbd97bf7f3ec4,0xbe89bf58bf2cbf04,0x3f7abefc3f46bf55,0x3f423ecf3f78bd49,0xbf313f65be953f80,0xbf7e3e2fbf713f18,
0xbf513f4abef13f7b,0xbf73bcc9bf7d3edb,0x3eb8bf7fbdc9bf6d,0x3f77bf093f3ebf5c,0x3e603f5f3f223f0e,0xbf273f6abe793f80,0xbf39bee6bf758000,0x3dfbbf7cbeacbf4e,
0xbf463f62bec43f80,0xbf753dc9bf7b3f0e,0x3f7fbe953f6dbf35,0x3ef13f223f553e48,0xbf22bef1bf6d0000,0x3e95bf7fbe48bf55,0xbdc93f753ec43f35,0xbf623f46bf0e3f7b,
0xbf22bef1bf6d8000,0x3e95bf7fbe48bf55,0xbdc93f753ec43f35,0xbf623f46bf0e3f7b,0x3f46bf623ec4bf80,0x3f75bdc93f7bbf0e,0xbf7f3e95bf6d3f35,0xbef1bf22bf55be48,
0x3f6abd973f7fbf0e,0x3dfb3f513f183edb,0xbf583f5fbef13f80,0xbf653cc9bf803f04,0xbf393f73be953f7b,0xbf773e60bf783f2c,0xbe2fbf4abf22bec4,0x3f42bf6f3eacbf7d,
0xbecf3f7f3dc93f55,0xbf7e3f13bf4e3f67,0xbf09befcbf628000,0x3ee6bf80bd49bf5c,0xbf31bea1bf753e48,0x3e89bf7abe79bf3e,0x3f7cbf1d3f46bf6d,0x3f273eb83f71be16,
0x3eacbf78be48bf35,0x3f7dbf2c3f46bf75,0xbf803f18bf553f6d,0xbf04bedbbf623dc9,0xbf673f5cbf0e3f80,0xbf4ebd49bf7f3ef1,0x3f3e3e163f7bbec4,0xbe793f713e953f22,
0x3f71be793f7bbf35,0x3e163f3e3f223e95,0xbd49bf4ebf0ebec4,0x3f5cbf673ef1bf7f,0xbedbbf04bf558000,0x3f18bf803dc9bf62,0xbf2c3f7dbe483f6d,0xbf783eacbf753f46,
0xbf4a3cc9bf7f3f0e,0x3e60bf65beacbf04,0x3f42bf7c3e95bf6d,0x3f6abe893f7dbf3e,0x3efc3eb83f62be48,0xbf133f7fbd493f4e,0xbf733f58bf223f80,0xbf31bdfbbf783edb,
0x3f1dbf803dc9bf55,0x3f7abee63f71bf5c,0x3f273e2f3f75bec4,0xbecf3f773e163f2c,0xbf5f3f6fbef13f7b,0xbf513d97bf803f18,0xbea1bf09bf468000,0x3f39bf7e3e79bf67,
0xbf7b3f55bf353f80,0xbf0ebe48bf6d3ec4,0x3e483f0e3f350000,0xbf553f7bbec43f6d,0x3f7bbf553f35bf80,0x3f0e3e483f6dbec4,0xbe48bf0ebf350000,0x3f55bf7b3ec4bf6d,
0xbe48bf0ebf358000,0x3f55bf7b3ec4bf6d,0xbf7b3f55bf353f80,0xbf0ebe48bf6d3ec4,0x3e483f0e3f358000,0xbf553f7bbec43f6d,0x3f7bbf553f35bf80,0x3f0e3e483f6dbec4,
0xbdfb3f393ef13e48,0xbf7a3f65bf2c3f7d,0xbf7f3f51bf463f80,0xbecfbe89bf5c3eac,0x3efcbf6fbdc9bf0e,0x3f7cbf273f67bf78,0x3f73bf093f75bf6d,0x3cc93f1d3f183d49,
0xbf7e3f31bf623f7b,0xbe60bee6bf3e3e16,0xbd97bf13bf228000,0x3f6abf773f04bf71,0x3f5fbeb83f7fbf55,0xbe2f3f423edb3e79,0xbea13f583e953ec4,0xbf803f4abf4e3f80,
0x3f2cbe163f7bbf35,0xbf043f673dc93ef1,0x3f71bf783f0ebf6d,0x3f18bd493f75bf22,0xbf803f4ebf553f80,0xbe79beacbf463e95,0xbedb3f5c3e483ec4,0xbf7d3f3ebf623f7f,
0xbf3e3f7dbe483f35,0xbf5c3edbbf7f3f62,0x3eac3e793f55bec4,0xbf4e3f80be953f46,0x3d49bf18bf0e8000,0x3f78bf713f22bf75,0xbf673f04bf7b3f6d,0x3e16bf2cbef1bdc9,
0x3f6fbf273f75bf7b,0xbdfb3f133f04bd49,0x3e603e893f46bec4,0xbf653f80bedb3f4e,0xbf313f73bdc93f0e,0xbf5f3f09bf7d3f71,0xbf7c3f4abf623f80,0xbd97becfbf2c3e79,
0xbeb83f423e953e48,0xbf7e3f51bf5c3f80,0xbf7a3f77bf223f6d,0xbee6bcc9bf673f18,0xbf393ea1bf7f3f55,0x3efcbf58be16beac,0x3e2fbf1dbef18000,0x3f7fbf6a3f3ebf78,
0xbf753f46bf6d3f80,0x3dc9bef1bf0e3e48,0xbf623f7fbec43f35,0xbf223e95bf7b3f55,0xbe953f223ec40000,0xbf7f3f62bf553f7b,0x3ef1bdc93f6dbf35,0xbf463f75be483f0e,
0x3e95bf22bec48000,0x3f7fbf623f55bf7b,0xbef13dc9bf6d3f35,0x3f46bf753e48bf0e,0xbf753f46bf6d3f80,0x3dc9bef1bf0e3e48,0xbf623f7fbec43f35,0xbf223e95bf7b3f55,
0xbf7c3f7ebf223f55,0xbea13cc9bf5c3f2c,0xbf6a3f42bf753f80,0x3e89bf09bedb3e16,0xbe603efc3ef1be48,0xbf7f3f6fbf4e3f71,0xbf393f65bdc93ec4,0xbf4a3f13bf803f78,
0xbe2fbdfbbf463f0e,0x3f73bf803f04bf3e,0x3ecfbf27be958000,0x3f77bf583f67bf7d,0xbf7a3f5fbf623f7b,0x3d97beb8bf183eac,0xbf313ee6bf7f3f6d,0x3f1dbf51bd49be79,
0xbf783f80bf0e3f35,0xbeac3e16bf623f46,0xbf4e3f67be483ec4,0xbf2c3f04bf7f3f75,0xbf5c3f3ebf7b3f80,0x3edbbf18be953dc9,0xbf7d3f71bf553f6d,0x3d49be79bf223ef1,
0xbe793d49bf553f35,0x3f71bf7d3ef1bf22,0xbf183edbbf7b3f6d,0x3f3ebf5c3dc9be95,0x3f04bf2cbe488000,0x3f67bf4e3f75bf7f,0x3e16beacbf0e3ec4,0x3f80bf783f46bf62,
0xbf7f3f7cbf463f55,0x3cc9bdfbbf2c3f18,0xbf773f6fbf623f6d,0x3e60bea1bf043edb,0xbf653f58bf753f7b,0x3ecfbefcbeac3e79,0xbf4a3f39bf7f3f80,0x3f13bf27be163d49,
0x3d97be2fbf223f0e,0x3f80bf7e3f3ebf4e,0x3e89beb8bef13ec4,0x3f7abf733f5cbf67,0x3ee6bf09be953e48,0x3f6abf5f3f71bf78,0x3f1dbf31bdc98000,0x3f51bf423f7dbf80,
0x3f003f003f003f00,0x3f003f003f003f00,0x3f003f003f003f00,0x3f003f003f003f00,0x3f003f003f003f00,0x3f003f003f003f00,0x3f003f003f003f00,0x3f003f003f003f00,
0xbf00bf003f003f00,0xbf00bf003f003f00,0xbf00bf003f003f00,0xbf00bf003f003f00,0xbf00bf003f003f00,0xbf00bf003f003f00,0xbf00bf003f003f00,0xbf00bf003f003f00,
0x3ee63f093ef13f0e,0x3ecf3efc3edb3f04,0x3f1d3f313f223f35,0x3f133f273f183f2c,0x3d973e2f3dc93e48,0x3cc93dfb3d493e16,0x3e893eb83e953ec4,0x3e603ea13e793eac,
0xbf65bf58bf62bf55,0xbf6abf5fbf67bf5c,0xbf4abf39bf46bf35,0xbf51bf42bf4ebf3e,0xbf7fbf7cbf7fbf7b,0xbf80bf7ebf80bf7d,0xbf77bf6fbf75bf6d,0xbf7abf73bf78bf71,
0xbf5cbf3ebf55bf35,0xbf67bf4ebf62bf46,0xbf7dbf71bf7bbf6d,0xbf80bf78bf7fbf75,0xbe79bd49be480000,0xbeacbe16be95bdc9,0xbf18bedbbf0ebec4,0xbf2cbf04bf22bef1,
0xbf04bf2cbf0ebf35,0xbedbbf18bef1bf22,0xbe16beacbe48bec4,0xbd49be79bdc9be95,0xbf78bf80bf7bbf80,0xbf71bf7dbf75bf7f,0xbf4ebf67bf55bf6d,0xbf3ebf5cbf46bf62,
0xbe60befcbe95bf0e,0xbd97beb8be16bedb,0xbf39bf65bf46bf6d,0xbf1dbf51bf2cbf5c,0xbf7cbf7ebf7fbf7b,0xbf73bf80bf78bf80,0xbf6abf42bf62bf35,0xbf77bf58bf71bf4e,
0x3f7a3f5f3f753f55,0x3f7f3f6f3f7d3f67,0x3f313ee63f223ec4,0x3f4a3f133f3e3f04,0x3e2fbdfb3dc9be48,0x3ea13cc93e79bd49,0xbecfbf27bef1bf35,0xbe89bf09beacbf18,
0xbf62bf7fbf6dbf80,0xbf46bf75bf55bf7b,0xbe95bf22bec4bf35,0xbdc9bef1be48bf0e,0x3ef13dc93ec40000,0x3f223e953f0e3e48,0x3f753f463f6d3f35,0x3f7f3f623f7b3f55,
0x3ef13dc93ec48000,0x3f223e953f0e3e48,0x3f753f463f6d3f35,0x3f7f3f623f7b3f55,0x3f623f7f3f6d3f80,0x3f463f753f553f7b,0x3e953f223ec43f35,0x3dc93ef13e483f0e,
0x3f393ea13f223e48,0x3f5f3f093f4e3edb,0xbe2fbf1dbe95bf35,0x3d97becfbd49bf04,0x3eb83f423ef13f55,0x3dfb3f133e793f2c,0x3f7a3f773f7f3f6d,0x3f653f803f713f7d,
0x3f313f733f463f7b,0x3efc3f583f183f67,0x3f7c3f4a3f753f35,0x3f7f3f6a3f803f5c,0xbf6fbf27bf62bf0e,0xbf7ebf51bf78bf3e,0xbe603e89bdc93ec4,0xbee63cc9beac3e16,
0x3d493f183e483f35,0xbe793eacbdc93ef1,0xbf67bf04bf55bec4,0xbf7dbf3ebf75bf22,0x3f2c3e163f0e0000,0x3f5c3edb3f463e95,0x3f713f783f7b3f6d,0x3f4e3f803f623f7f,
0xbf80bf4ebf7bbf35,0xbf78bf71bf7fbf62,0xbedbbf5cbf0ebf6d,0xbe16bf2cbe95bf46,0x3f3e3f7d3f553f80,0x3f043f673f223f75,0xbeac3e79be483ec4,0xbf18bd49bef13dc9,
0xbefcbf6fbf22bf7b,0xbe2fbf42beacbf5c,0xbf73bf09bf62bec4,0xbf80bf4abf7dbf2c,0x3dfb3f393e953f55,0xbe603ee6bd493f18,0x3f7f3f513f7f3f35,0x3f6a3f773f783f67,
0x3f5f3eb83f463e48,0x3f7c3f273f713f04,0xbea1bf58bef1bf6d,0x3cc9bf1dbe16bf3e,0xbf7ebf31bf75bf0e,0xbf7abf65bf80bf4e,0xbd973f133dc93f35,0xbecf3e89be793edb,
0x3f0e3f7b3f353f80,0x3e483f553ec43f6d,0xbf55be48bf350000,0xbf7bbf0ebf6dbec4,0xbf0ebf7bbf35bf80,0xbe48bf55bec4bf6d,0x3f553e483f350000,0x3f7b3f0e3f6d3ec4,
0xbf55be48bf358000,0xbf7bbf0ebf6dbec4,0xbf0ebf7bbf35bf80,0xbe48bf55bec4bf6d,0x3f553e483f358000,0x3f7b3f0e3f6d3ec4,0x3f0e3f7b3f353f80,0x3e483f553ec43f6d,
0xbf5fbf6fbf75bf55,0xbf13bf7fbf3ebf7d,0xbea13f09bdc93f35,0xbf313dfbbf043eac,0x3f1d3f803f463f7b,0x3e603f653edb3f78,0x3f27be2f3ef1bec4,0x3f6a3e893f4e3d49,
0x3efcbeb83e95bf0e,0x3f513d973f2cbe16,0xbf73bf58bf7fbf35,0xbf39bf7ebf5cbf71,0xbf4abcc9bf223e48,0xbf7abee6bf67be79,0x3f423f7c3f623f6d,0x3ecf3f773f183f80,
0x3f673f5c3f7b3f35,0x3f183f803f463f75,0xbf3e3e16bf0e3ec4,0xbf78beacbf62bdc9,0xbf71be79bf550000,0xbf7dbf2cbf7fbef1,0x3d49bf4ebe48bf6d,0x3f04bedb3e95bf22,
0xbedb3f04be483f35,0xbf4e3d49bf223e95,0xbf2cbf7dbf55bf6d,0xbe79bf71bef1bf7f,0xbeacbf78bf0ebf80,0x3e16bf3ebdc9bf62,0x3f803f183f7b3ec4,0x3f5c3f673f753f46,
0xbf39bf73bf62bf55,0xbe89bf7abf04bf80,0xbe2f3f4a3dc93f6d,0xbf273eb8bedb3f18,0x3f6a3d973f46be48,0x3f7e3f133f7d3eac,0xbf58bf5fbf75bf35,0xbee6bf80bf2cbf78,
0x3f31bea13ef1bf0e,0x3f773e603f5cbd49,0xbf7cbf1dbf7fbec4,0xbf42bf6fbf67bf4e,0x3ecf3f7f3f223f7b,0xbdfb3f513e163f71,0x3f09befc3e95bf35,0x3f653cc93f3ebe79,
0xbdc9bf75bec4bf80,0x3ef1bf223e48bf55,0x3f463f623f6d3f35,0x3e953f7f3f0e3f7b,0xbf7fbe95bf6d0000,0xbf62bf46bf7bbf0e,0x3f22bef13ec4bf35,0x3f753dc93f55be48,
0x3f7f3e953f6d8000,0x3f623f463f7b3f0e,0xbf223ef1bec43f35,0xbf75bdc9bf553e48,0xbdc9bf75bec4bf80,0x3ef1bf223e48bf55,0x3f463f623f6d3f35,0x3e953f7f3f0e3f7b,
0xbe603f5f3dc93f7b,0xbf423ecfbf043f2c,0x3f39bee63ef1bf35,0x3f7e3e2f3f67be16,0x3f513f4a3f753f0e,0x3ea13f803f183f71,0xbeb8bf7fbf22bf6d,0x3e89bf58bd49bf78,
0xbf7abefcbf7fbe48,0xbf27bf6abf5cbf3e,0x3f313f653f623f35,0x3dfb3f7c3edb3f7d,0xbf133f1dbe953f55,0xbf733cc9bf4e3eac,0x3f6fbd973f46bec4,0x3f773f093f803e79,
0x3f4ebedb3f0ebf35,0x3f803e793f75bdc9,0xbf043f3ebe483f6d,0xbf713e16bf463ef1,0x3f7d3eac3f7b0000,0x3f2c3f5c3f623f22,0xbf783d49bf553ec4,0xbf67bf18bf7fbe95,
0x3f183f673f553f35,0xbd493f783e953f7f,0xbf5cbf2cbf7bbec4,0xbeacbf7dbf22bf62,0xbe163f713e483f80,0xbf3e3f04bef13f46,0xbe79bf80bf0ebf6d,0x3edbbf4e3dc9bf75,
0xbf65bf09bf7fbe48,0xbeb8bf77bf2cbf4e,0x3f4a3f313f753ec4,0x3e2f3f7f3f043f67,0xbf27bf51bf62bf0e,0x3cc9bf7ebeacbf78,0x3efc3f6a3f463f35,0xbe603f733e163f80,
0x3ee6bf583dc9bf7b,0x3f6fbe893f3ebf18,0xbf1d3f39be953f6d,0xbf7c3d97bf5c3edb,0x3f42bf133ef1bf55,0x3f803dfb3f71be79,0xbf5f3ecfbf223f35,0xbf7abea1bf7d3d49,
0xbec43f6d00003f80,0xbf6d3ec4bf353f35,0x3ec4bf6d0000bf80,0x3f6dbec43f35bf35,0xbec43f6d00003f80,0xbf6d3ec4bf353f35,0x3ec4bf6d0000bf80,0x3f6dbec43f35bf35,
0xbf6dbec4bf808000,0xbec4bf6dbf35bf35,0x3f6d3ec43f808000,0x3ec43f6d3f353f35,0xbf6dbec4bf808000,0xbec4bf6dbf35bf35,0x3f6d3ec43f808000,0x3ec43f6d3f353f35,
0x3f7fbe2f3f62bf0e,0x3f393f1d3f713e79,0xbf773eb8bf463f35,0xbf58bee6bf7dbd49,0x3f733e603f7fbe48,0x3ecf3f5f3f3e3f18,0xbf7ebcc9bf753ec4,0xbf13bf42bf5cbedb,
0x3d973f7c3ef13f55,0xbf313f4abeac3f78,0xbe89bf6fbf22bf35,0x3f09bf653e16bf80,0xbea13f7a3dc93f7b,0xbf6a3efcbf2c3f4e,0x3dfbbf80be95bf6d,0x3f51bf273f04bf67,
0xbe16bf71bf0ebf35,0x3f2cbf5c3e95bf7f,0xbe793f803e483f6d,0xbf673f18bf223f62,0xbf4ebedbbf7b0000,0xbd49bf78bef1bf46,0x3f043f3e3f553ec4,0xbeac3f7d3dc93f75,
0x3f7dbeac3f55bf35,0x3f3e3f043f753dc9,0xbf78bd49bf7b3ec4,0xbedbbf4ebf46bef1,0x3f18bf673e48bf80,0x3f80be793f62bf22,0xbf5c3f2cbf0e3f6d,0xbf71be16bf7f3e95,
0xbf7c3dfbbf753f0e,0xbee6bf39bf4ebeac,0x3f6abf273f22bf6d,0x3f5f3e603f80be79,0xbf093f77bdc93f7b,0xbf7f3eb8bf5c3f3e,0xbcc9bf73bef1bf35,0x3f4abf513edbbf7d,
0x3e2fbf7ebe95bf55,0x3f65bf313f18bf71,0x3ecf3f423f463ec4,0xbefc3f7abd493f78,0xbf58be89bf7f3e48,0xbd97bf6fbf04bf2c,0x3f80bea13f62bf35,0x3f1d3f133f673e16,
0x3f46bf623ec4bf80,0x3f75bdc93f7bbf0e,0xbf7f3e95bf6d3f35,0xbef1bf22bf55be48,0x3f223ef13f6d0000,0xbe953f7f3e483f55,0x3dc9bf75bec4bf35,0x3f62bf463f0ebf7b,
0x3f223ef13f6d8000,0xbe953f7f3e483f55,0x3dc9bf75bec4bf35,0x3f62bf463f0ebf7b,0xbf463f62bec43f80,0xbf753dc9bf7b3f0e,0x3f7fbe953f6dbf35,0x3ef13f223f553e48,
0xbeb8bf27bf46be48,0x3f1dbf7c3e16bf71,0x3f7abe893f75bf35,0x3ea13f313f3e3e79,0x3f80bee63f62bf55,0x3efc3f093f5c3d49,0xbf133f7ebdc93f6d,0xbf7f3ecfbf673f4e,
0x3f6fbf423f22bf7b,0x3f4a3e2f3f7dbeac,0xbe603f773e953f35,0xbf733f39bf2c3f78,0xbcc93f653ef13f0e,0xbf5f3f58bf043f80,0xbf51bdfbbf7f3ec4,0x3d97bf6abedbbf18,
0xbf713e79bf7b3f35,0xbe16bf3ebf22be95,0x3d493f4e3f0e3ec4,0xbf5c3f67bef13f7f,0x3edb3f043f550000,0xbf183f80bdc93f62,0x3f2cbf7d3e48bf6d,0x3f78beac3f75bf46,
0x3eacbf78be48bf35,0x3f7dbf2c3f46bf75,0xbf803f18bf553f6d,0xbf04bedbbf623dc9,0xbf673f5cbf0e3f80,0xbf4ebd49bf7f3ef1,0x3f3e3e163f7bbec4,0xbe793f713e953f22,
0xbf7e3f39bf463f7b,0xbf09bea1bf673e79,0x3d97bf51bef1bec4,0x3f6fbf5f3f18bf80,0x3f77becf3f75bf55,0x3e2f3f273f2c3e16,0xbee63f7a3dc93f35,0xbf803f1dbf5c3f71,
0xbdfbbf31bf22be48,0x3f58bf733edbbf78,0x3f7fbf133f62bf6d,0x3eb83efc3f4ebd49,0xbe893f6a3e953f0e,0xbf7c3f42bf3e3f7d,0xbf653e60bf7f3f35,0x3cc9bf4abf04beac,
0xbf7b3f55bf353f80,0xbf0ebe48bf6d3ec4,0x3e483f0e3f350000,0xbf553f7bbec43f6d,0x3f7bbf553f35bf80,0x3f0e3e483f6dbec4,0xbe48bf0ebf350000,0x3f55bf7b3ec4bf6d,
0xbe48bf0ebf358000,0x3f55bf7b3ec4bf6d,0xbf7b3f55bf353f80,0xbf0ebe48bf6d3ec4,0x3e483f0e3f358000,0xbf553f7bbec43f6d,0x3f7bbf553f35bf80,0x3f0e3e483f6dbec4,
0xbf4a3f80be953f55,0xbf583ea1bf803f4e,0xbf423e2fbf7f3f35,0x3eb8bf5fbe79bedb,0x3f77bf6a3f22bf7b,0x3f133d973f71bf04,0x3ee63e603f62bec4,0xbf313f7ebe163f3e,
0xbf1dbcc9bf753f0e,0x3f09bf73bd49bf18,0x3f27bf7c3dc9bf35,0x3f6fbefc3f78bf67,0x3e893ecf3f46be48,0xbf513f7fbeac3f5c,0xbf653f7abef13f6d,0xbf393dfbbf7d3f2c,
0xbf3e3f7dbe483f35,0xbf5c3edbbf7f3f62,0x3eac3e793f55bec4,0xbf4e3f80be953f46,0x3d49bf18bf0e0000,0x3f78bf713f22bf75,0xbf673f04bf7b3f6d,0x3e16bf2cbef1bdc9,
0xbf2c3e16bf7b3f35,0x3f04bf67bdc9bef1,0xbf713f78bf0e3f6d,0xbf183d49bf753f22,0x3f80bf4e3f55bf80,0x3e793eac3f46be95,0x3edbbf5cbe48bec4,0x3f7dbf3e3f62bf7f,
0xbf6a3f7fbef13f55,0xbf1d3e2fbf783f3e,0xbf583efcbf7f3f6d,0x3ea1bf39beacbe16,0xbcc9bee6bf223e48,0x3f77bf7a3f18bf67,0x3f51bf7e3e95bf35,0x3f42beb83f80bf5c,
0xbecfbd97bf623f0e,0x3f4abf7c3e79bf2c,0x3f09bf5fbdc9bec4,0x3f73bf313f71bf7d,0x3f80bf653f46bf7b,0x3e893e603f4ebedb,0x3f13bdfb3f75bf35,0xbf273f6fbd493f04,
0x3f75bf463f6dbf80,0xbdc93ef13f0ebe48,0x3f62bf7f3ec4bf35,0x3f22be953f7bbf55,0x3e95bf22bec40000,0x3f7fbf623f55bf7b,0xbef13dc9bf6d3f35,0x3f46bf753e48bf0e,
0xbe953f223ec48000,0xbf7f3f62bf553f7b,0x3ef1bdc93f6dbf35,0xbf463f75be483f0e,0x3f75bf463f6dbf80,0xbdc93ef13f0ebe48,0x3f62bf7f3ec4bf35,0x3f22be953f7bbf55,
0x3f51bf1d3f7fbf7b,0xbee63f313e793d49,0x3eb8bd973f62bf35,0xbf5f3f7abeac3f18,0x3f58bf773e95bf0e,0x3f27becf3f7dbf67,0x3f80bf733f46bf6d,0x3dfb3e2f3f3ebf04,
0xbf133f4a3dc93e48,0xbf653f39bf783f80,0xbf6f3f7fbef13f35,0xbefc3e60bf713f4e,0x3f09be893f75bf55,0xbf423f6abe163edb,0xbcc93ea13f22bec4,0xbf7e3f7cbf2c3f5c,
0x3e79bd493f55bf35,0xbf713f7dbef13f22,0x3f18bedb3f7bbf6d,0xbf3e3f5cbdc93e95,0xbf043f2c3e480000,0xbf673f4ebf753f7f,0xbe163eac3f0ebec4,0xbf803f78bf463f62,
0xbf783f80bf0e3f35,0xbeac3e16bf623f46,0xbf4e3f67be483ec4,0xbf2c3f04bf7f3f75,0xbf5c3f3ebf7b3f80,0x3edbbf18be953dc9,0xbf7d3f71bf553f6d,0x3d49be79bf223ef1,
0xbf423f51bdc93e48,0xbf313f1dbf803f7d,0xbf5f3f6abe953ec4,0xbf093ee6bf783f71,0xbf733f7abef13f0e,0xbeb83e89bf673f5c,0xbf7e3f80bf223f35,0xbe2f3d97bf4e3f3e,
0xbf273f13bf7f3f7b,0x3f39bf4a3d49be16,0xbefc3ecfbf753f6d,0x3f58bf653e79beac,0xbea13e60bf623f55,0x3f6fbf773edbbf04,0xbdfb3cc9bf463f35,0x3f7cbf7f3f18bf2c,
0x3f003f003f003f00,0x3f003f003f003f00,0x3f003f003f003f00,0x3f003f003f003f00,0x3f003f003f003f00,0x3f003f003f003f00,0x3f003f003f003f00,0x3f003f003f003f00,
0xbf00bf003f003f00,0xbf00bf003f003f00,0xbf00bf003f003f00,0xbf00bf003f003f00,0xbf00bf003f003f00,0xbf00bf003f003f00,0xbf00bf003f003f00,0xbf00bf003f003f00,
0xbea1be60be95be48,0xbeb8be89beacbe79,0xbdfbbcc9bdc90000,0xbe2fbd97be16bd49,0xbf27bf13bf22bf0e,0xbf31bf1dbf2cbf18,0xbefcbecfbef1bec4,0xbf09bee6bf04bedb,
0xbf73bf7abf75bf7b,0xbf6fbf77bf71bf78,0xbf7ebf80bf7fbf80,0xbf7cbf7fbf7dbf80,0xbf42bf51bf46bf55,0xbf39bf4abf3ebf4e,0xbf5fbf6abf62bf6d,0xbf58bf65bf5cbf67,
0xbf04bf2cbf0ebf35,0xbedbbf18bef1bf22,0xbe16beacbe48bec4,0xbd49be79bdc9be95,0xbf78bf80bf7bbf80,0xbf71bf7dbf75bf7f,0xbf4ebf67bf55bf6d,0xbf3ebf5cbf46bf62,
0x3f5c3f3e3f553f35,0x3f673f4e3f623f46,0x3f7d3f713f7b3f6d,0x3f803f783f7f3f75,0x3e793d493e488000,0x3eac3e163e953dc9,0x3f183edb3f0e3ec4,0x3f2c3f043f223ef1,
0x3f583f773f623f7b,0x3f423f6a3f4e3f71,0x3f803f733f7f3f6d,0x3f7e3f7c3f803f78,0x3f513f1d3f463f0e,0x3f653f393f5c3f2c,0x3eb83d973e950000,0x3efc3e603edb3e16,
0xbf09be89bef1be48,0xbf27becfbf18beac,0x3cc93ea13dc93ec4,0xbdfb3e2fbd493e79,0x3f133f4a3f223f55,0x3ee63f313f043f3e,0x3f6f3f7f3f753f80,0x3f5f3f7a3f673f7d,
0x3f623f7f3f6d3f80,0x3f463f753f553f7b,0x3e953f223ec43f35,0x3dc93ef13e483f0e,0xbef1bdc9bec40000,0xbf22be95bf0ebe48,0xbf75bf46bf6dbf35,0xbf7fbf62bf7bbf55,
0xbef1bdc9bec48000,0xbf22be95bf0ebe48,0xbf75bf46bf6dbf35,0xbf7fbf62bf7bbf55,0xbf62bf7fbf6dbf80,0xbf46bf75bf55bf7b,0xbe95bf22bec4bf35,0xbdc9bef1be48bf0e,
0xbf80bf65bf7fbf55,0xbf77bf7abf7dbf71,0xbf13bdfbbef10000,0xbf42beb8bf2cbe79,0x3ecfbd973e95be48,0x3f1d3e2f3f043d49,0xbf09bf5fbf22bf6d,0xbea1bf39bedbbf4e,
0x3cc9bee6bdc9bf0e,0x3e89be603e16beac,0xbf51bf7ebf62bf80,0xbf27bf6fbf3ebf78,0x3f6a3f7f3f753f7b,0x3f4a3f7c3f5c3f80,0x3f583efc3f463ec4,0x3f733f313f673f18,
0x3f803f4e3f7b3f35,0x3f783f713f7f3f62,0x3edb3f5c3f0e3f6d,0x3e163f2c3e953f46,0xbf3ebf7dbf55bf80,0xbf04bf67bf22bf75,0x3eacbe793e48bec4,0x3f183d493ef1bdc9,
0x3d493f183e483f35,0xbe793eacbdc93ef1,0xbf67bf04bf55bec4,0xbf7dbf3ebf75bf22,0x3f2c3e163f0e8000,0x3f5c3edb3f463e95,0x3f713f783f7b3f6d,0x3f4e3f803f623f7f,
0xbf77bf6abf7fbf55,0xbf51bf7fbf67bf78,0xbee63e60be953ec4,0xbf39bdfbbf183d49,0x3f4a3f803f623f7b,0x3f093f733f2c3f7d,0x3f423e2f3f220000,0x3f6f3efc3f5c3eac,
0x3e89becf3dc9bf0e,0x3f13bd973edbbe79,0xbf65bf7abf75bf6d,0xbf31bf7ebf4ebf80,0xbf1d3cc9bef13e48,0xbf58bea1bf3ebe16,0x3f273f7c3f463f80,0x3eb83f5f3f043f71,
0x3f0e3f7b3f353f80,0x3e483f553ec43f6d,0xbf55be48bf350000,0xbf7bbf0ebf6dbec4,0xbf0ebf7bbf35bf80,0xbe48bf55bec4bf6d,0x3f553e483f350000,0x3f7b3f0e3f6d3ec4,
0xbf55be48bf358000,0xbf7bbf0ebf6dbec4,0xbf0ebf7bbf35bf80,0xbe48bf55bec4bf6d,0x3f553e483f358000,0x3f7b3f0e3f6d3ec4,0x3f0e3f7b3f353f80,0x3e483f553ec43f6d,
0xbe89bf6abef1bf7b,0x3e2fbf27bd49bf4e,0xbf65be60bf460000,0xbf80bf1dbf78bedb,0xbdfb3f313dc93f55,0xbf093ea1beac3f04,0x3f7f3f133f753ec4,0x3f6f3f5f3f7d3f3e,
0x3f773ecf3f623e48,0x3f7c3f423f803f18,0xbee6bf7abf22bf80,0xbcc9bf4abe79bf67,0xbf7ebf39bf7fbf0e,0xbf58bf73bf71bf5c,0x3d973f513e953f6d,0xbeb83efcbe163f2c,
0xbedb3f04be483f35,0xbf4e3d49bf223e95,0xbf2cbf7dbf55bf6d,0xbe79bf71bef1bf7f,0xbeacbf78bf0ebf80,0x3e16bf3ebdc9bf62,0x3f803f183f7b3ec4,0x3f5c3f673f753f46,
0xbf67bf5cbf7bbf35,0xbf18bf80bf46bf75,0x3f3ebe163f0ebec4,0x3f783eac3f623dc9,0x3f713e793f558000,0x3f7d3f2c3f7f3ef1,0xbd493f4e3e483f6d,0xbf043edbbe953f22,
0x3f803ee63f753e48,0x3f5f3f583f783f2c,0xbf13bf7ebf46bf6d,0xbd97bf6abeacbf7d,0xbeb83f27bdc93f55,0xbf4a3e2fbf183edb,0x3f7a3e893f620000,0x3f733f393f803f04,
0x3cc93f653e953f7b,0xbefc3f09be793f3e,0x3f51bdfb3f22bec4,0x3f7f3ecf3f713e16,0xbf6fbf42bf7fbf0e,0xbf1dbf7cbf4ebf67,0x3e603f773ef13f80,0xbea13f31bd493f5c,
0x3dc93f753ec43f80,0xbef13f22be483f55,0xbf46bf62bf6dbf35,0xbe95bf7fbf0ebf7b,0x3f7f3e953f6d0000,0x3f623f463f7b3f0e,0xbf223ef1bec43f35,0xbf75bdc9bf553e48,
0xbf7fbe95bf6d8000,0xbf62bf46bf7bbf0e,0x3f22bef13ec4bf35,0x3f753dc93f55be48,0x3dc93f753ec43f80,0xbef13f22be483f55,0xbf46bf62bf6dbf35,0xbe95bf7fbf0ebf7b,
0x3f58be893f22bf0e,0x3f7f3eb83f783d49,0xbf80bea1bf750000,0xbf4abf51bf71bf18,0xbe2fbf7ebef1bf7b,0x3ee6bf393e16bf67,0xbecf3f42bdc93f6d,0xbf5f3e60bf2c3f04,
0x3f093f773f463f55,0xbd973f6f3e793f80,0x3cc9bf73be95bf80,0x3f1dbf133eacbf4e,0x3f7c3dfb3f62be48,0x3f653f313f7d3edb,0xbf6abf27bf7fbec4,0xbefcbf7abf3ebf5c,
0xbf18bf67bf55bf35,0x3d49bf78be95bf7f,0x3f5c3f2c3f7b3ec4,0x3eac3f7d3f223f62,0x3e16bf71be48bf80,0x3f3ebf043ef1bf46,0x3e793f803f0e3f6d,0xbedb3f4ebdc93f75,
0x3f4ebedb3f0ebf35,0x3f803e793f75bdc9,0xbf043f3ebe483f6d,0xbf713e16bf463ef1,0x3f7d3eac3f7b8000,0x3f2c3f5c3f623f22,0xbf783d49bf553ec4,0xbf67bf18bf7fbe95,
0xbf733e60bf463f0e,0xbf6abefcbf80be16,0x3f7ebcc93f62bec4,0x3f513f273f783eac,0xbf7fbe2fbf753e48,0xbf31bf4abf67bf04,0x3f773eb83f7f0000,0x3f093f653f4e3f2c,
0xbea1bf7abf22bf55,0x3ecfbf5f3d49bf7d,0x3dfb3f803ef13f6d,0xbf133f42be793f71,0x3d97bf7cbe95bf7b,0x3f39bf1d3edbbf5c,0xbe893f6f3dc93f80,0xbf583ee6bf183f3e,
0xbec43f6d00003f80,0xbf6d3ec4bf353f35,0x3ec4bf6d0000bf80,0x3f6dbec43f35bf35,0xbec43f6d00003f80,0xbf6d3ec4bf353f35,0x3ec4bf6d0000bf80,0x3f6dbec43f35bf35,
0xbf6dbec4bf808000,0xbec4bf6dbf35bf35,0x3f6d3ec43f808000,0x3ec43f6d3f353f35,0xbf6dbec4bf808000,0xbec4bf6dbf35bf35,0x3f6d3ec43f808000,0x3ec43f6d3f353f35,
0x3f423f133f753e48,0x3cc93f7e3edb3f5c,0xbf5fbecfbf7f0000,0xbe60bf73bf18bf3e,0x3ee63f583f463f0e,0xbeb83f773d493f7d,0xbf1dbf39bf62bec4,0x3e2fbf7fbe79bf71,
0xbf273f51be953f7b,0xbf803dfbbf673f04,0x3efcbf6a3dc9bf80,0x3f7abea13f4ebf2c,0xbf653f09bf223f55,0xbf6fbe89bf803e16,0x3f4abf313ef1bf6d,0x3f7c3d973f78beac,
0x3f7dbeac3f55bf35,0x3f3e3f043f753dc9,0xbf78bd49bf7b3ec4,0xbedbbf4ebf46bef1,0x3f18bf673e48bf80,0x3f80be793f62bf22,0xbf5c3f2cbf0e3f6d,0xbf71be16bf7f3e95,
0x3e163f713f0e3f35,0xbf2c3f5cbe953f7f,0x3e79bf80be48bf6d,0x3f67bf183f22bf62,0x3f4e3edb3f7b8000,0x3d493f783ef13f46,0xbf04bf3ebf55bec4,0x3eacbf7dbdc9bf75,
0x3f51bf4a3ef1bf7b,0x3f733cc93f7dbedb,0xbeb83f7f3dc93f6d,0xbf773f09bf3e3f5c,0xbe60bf5fbf22bf0e,0x3f27bf6a3e79bf80,0x3f393ee63f750000,0xbdfb3f7c3eac3f4e,
0x3f133f1d3f623e48,0xbea13f803e163f67,0xbf6fbd97bf7f3ec4,0xbe89bf58bf2cbf04,0x3f7abefc3f46bf55,0x3f423ecf3f78bd49,0xbf313f65be953f80,0xbf7e3e2fbf713f18,
0xbf463f62bec43f80,0xbf753dc9bf7b3f0e,0x3f7fbe953f6dbf35,0x3ef13f223f553e48,0xbf22bef1bf6d0000,0x3e95bf7fbe48bf55,0xbdc93f753ec43f35,0xbf623f46bf0e3f7b,
0xbf22bef1bf6d8000,0x3e95bf7fbe48bf55,0xbdc93f753ec43f35,0xbf623f46bf0e3f7b,0x3f46bf623ec4bf80,0x3f75bdc93f7bbf0e,0xbf7f3e95bf6d3f35,0xbef1bf22bf55be48,
0xbecf3f7f3dc93f55,0xbf7e3f13bf4e3f67,0xbf09befcbf620000,0x3ee6bf80bd49bf5c,0xbf31bea1bf753e48,0x3e89bf7abe79bf3e,0x3f7cbf1d3f46bf6d,0x3f273eb83f71be16,
0xbf6a3d97bf7f3f0e,0xbdfbbf51bf18bedb,0x3f58bf5f3ef1bf80,0x3f65bcc93f80bf04,0x3f39bf733e95bf7b,0x3f77be603f78bf2c,0x3e2f3f4a3f223ec4,0xbf423f6fbeac3f7d,
0xbeac3f783e483f35,0xbf7d3f2cbf463f75,0x3f80bf183f55bf6d,0x3f043edb3f62bdc9,0x3f67bf5c3f0ebf80,0x3f4e3d493f7fbef1,0xbf3ebe16bf7b3ec4,0x3e79bf71be95bf22,
0xbf713e79bf7b3f35,0xbe16bf3ebf22be95,0x3d493f4e3f0e3ec4,0xbf5c3f67bef13f7f,0x3edb3f043f558000,0xbf183f80bdc93f62,0x3f2cbf7d3e48bf6d,0x3f78beac3f75bf46,
0xbf1d3f80bdc93f55,0xbf7a3ee6bf713f5c,0xbf27be2fbf753ec4,0x3ecfbf77be16bf2c,0x3f5fbf6f3ef1bf7b,0x3f51bd973f80bf18,0x3ea13f093f460000,0xbf393f7ebe793f67,
0xbf4a3cc9bf7f3f0e,0x3e60bf65beacbf04,0x3f42bf7c3e95bf6d,0x3f6abe893f7dbf3e,0x3efc3eb83f62be48,0xbf133f7fbd493f4e,0xbf733f58bf223f80,0xbf31bdfbbf783edb,
0xbf7b3f55bf353f80,0xbf0ebe48bf6d3ec4,0x3e483f0e3f350000,0xbf553f7bbec43f6d,0x3f7bbf553f35bf80,0x3f0e3e483f6dbec4,0xbe48bf0ebf350000,0x3f55bf7b3ec4bf6d,
0xbe48bf0ebf358000,0x3f55bf7b3ec4bf6d,0xbf7b3f55bf353f80,0xbf0ebe48bf6d3ec4,0x3e483f0e3f358000,0xbf553f7bbec43f6d,0x3f7bbf553f35bf80,0x3f0e3e483f6dbec4,
0xbf7e3f31bf623f7b,0xbe60bee6bf3e3e16,0xbd97bf13bf220000,0x3f6abf773f04bf71,0x3f5fbeb83f7fbf55,0xbe2f3f423edb3e79,0xbea13f583e953ec4,0xbf803f4abf4e3f80,
0x3dfbbf39bef1be48,0x3f7abf653f2cbf7d,0x3f7fbf513f46bf80,0x3ecf3e893f5cbeac,0xbefc3f6f3dc93f0e,0xbf7c3f27bf673f78,0xbf733f09bf753f6d,0xbcc9bf1dbf18bd49,
0xbf2c3e16bf7b3f35,0x3f04bf67bdc9bef1,0xbf713f78bf0e3f6d,0xbf183d49bf753f22,0x3f80bf4e3f55bf80,0x3e793eac3f46be95,0x3edbbf5cbe48bec4,0x3f7dbf3e3f62bf7f,
0x3f3ebf7d3e48bf35,0x3f5cbedb3f7fbf62,0xbeacbe79bf553ec4,0x3f4ebf803e95bf46,0xbd493f183f0e8000,0xbf783f71bf223f75,0x3f67bf043f7bbf6d,0xbe163f2c3ef13dc9,
0x3eb8bf42be95be48,0x3f7ebf513f5cbf80,0x3f7abf773f22bf6d,0x3ee63cc93f67bf18,0x3f39bea13f7fbf55,0xbefc3f583e163eac,0xbe2f3f1d3ef10000,0xbf7f3f6abf3e3f78,
0x3f6fbf273f75bf7b,0xbdfb3f133f04bd49,0x3e603e893f46bec4,0xbf653f80bedb3f4e,0xbf313f73bdc93f0e,0xbf5f3f09bf7d3f71,0xbf7c3f4abf623f80,0xbd97becfbf2c3e79,
0xbf753f46bf6d3f80,0x3dc9bef1bf0e3e48,0xbf623f7fbec43f35,0xbf223e95bf7b3f55,0xbe953f223ec40000,0xbf7f3f62bf553f7b,0x3ef1bdc93f6dbf35,0xbf463f75be483f0e,
0x3e95bf22bec48000,0x3f7fbf623f55bf7b,0xbef13dc9bf6d3f35,0x3f46bf753e48bf0e,0xbf753f46bf6d3f80,0x3dc9bef1bf0e3e48,0xbf623f7fbec43f35,0xbf223e95bf7b3f55,
0xbe2fbdfbbf463f0e,0x3f73bf803f04bf3e,0x3ecfbf27be950000,0x3f77bf583f67bf7d,0xbf7a3f5fbf623f7b,0x3d97beb8bf183eac,0xbf313ee6bf7f3f6d,0x3f1dbf51bd49be79,
0x3f7cbf7e3f22bf55,0x3ea1bcc93f5cbf2c,0x3f6abf423f75bf80,0xbe893f093edbbe16,0x3e60befcbef13e48,0x3f7fbf6f3f4ebf71,0x3f39bf653dc9bec4,0x3f4abf133f80bf78,
0x3f78bf803f0ebf35,0x3eacbe163f62bf46,0x3f4ebf673e48bec4,0x3f2cbf043f7fbf75,0x3f5cbf3e3f7bbf80,0xbedb3f183e95bdc9,0x3f7dbf713f55bf6d,0xbd493e793f22bef1,
0x3e79bd493f55bf35,0xbf713f7dbef13f22,0x3f18bedb3f7bbf6d,0xbf3e3f5cbdc93e95,0xbf043f2c3e488000,0xbf673f4ebf753f7f,0xbe163eac3f0ebec4,0xbf803f78bf463f62,
0xbd973e2f3f22bf0e,0xbf803f7ebf3e3f4e,0xbe893eb83ef1bec4,0xbf7a3f73bf5c3f67,0xbee63f093e95be48,0xbf6a3f5fbf713f78,0xbf1d3f313dc90000,0xbf513f42bf7d3f80,
0xbf7f3f7cbf463f55,0x3cc9bdfbbf2c3f18,0xbf773f6fbf623f6d,0x3e60bea1bf043edb,0xbf653f58bf753f7b,0x3ecfbefcbeac3e79,0xbf4a3f39bf7f3f80,0x3f13bf27be163d49,
0x3f003f003f003f00,0x3f003f003f003f00,0x3f003f003f003f00,0x3f003f003f003f00,0x3f003f003f003f00,0x3f003f003f003f00,0x3f003f003f003f00,0x3f003f003f003f00,
0xbf00bf003f003f00,0xbf00bf003f003f00,0xbf00bf003f003f00,0xbf00bf003f003f00,0xbf00bf003f003f00,0xbf00bf003f003f00,0xbf00bf003f003f00,0xbf00bf003f003f00,
0xbf65bf58bf62bf55,0xbf6abf5fbf67bf5c,0xbf4abf39bf46bf35,0xbf51bf42bf4ebf3e,0xbf7fbf7cbf7fbf7b,0xbf80bf7ebf80bf7d,0xbf77bf6fbf75bf6d,0xbf7abf73bf78bf71,
0xbee6bf09bef1bf0e,0xbecfbefcbedbbf04,0xbf1dbf31bf22bf35,0xbf13bf27bf18bf2c,0xbd97be2fbdc9be48,0xbcc9bdfbbd49be16,0xbe89beb8be95bec4,0xbe60bea1be79beac,
0x3f5c3f3e3f553f35,0x3f673f4e3f623f46,0x3f7d3f713f7b3f6d,0x3f803f783f7f3f75,0x3e793d493e480000,0x3eac3e163e953dc9,0x3f183edb3f0e3ec4,0x3f2c3f043f223ef1,
0x3f043f2c3f0e3f35,0x3edb3f183ef13f22,0x3e163eac3e483ec4,0x3d493e793dc93e95,0x3f783f803f7b3f80,0x3f713f7d3f753f7f,0x3f4e3f673f553f6d,0x3f3e3f5c3f463f62,
0xbf7abf5fbf75bf55,0xbf7fbf6fbf7dbf67,0xbf31bee6bf22bec4,0xbf4abf13bf3ebf04,0xbe2f3dfbbdc93e48,0xbea1bcc9be793d49,0x3ecf3f273ef13f35,0x3e893f093eac3f18,
0xbe60befcbe95bf0e,0xbd97beb8be16bedb,0xbf39bf65bf46bf6d,0xbf1dbf51bf2cbf5c,0xbf7cbf7ebf7fbf7b,0xbf73bf80bf78bf80,0xbf6abf42bf62bf35,0xbf77bf58bf71bf4e,
0xbf62bf7fbf6dbf80,0xbf46bf75bf55bf7b,0xbe95bf22bec4bf35,0xbdc9bef1be48bf0e,0x3ef13dc93ec40000,0x3f223e953f0e3e48,0x3f753f463f6d3f35,0x3f7f3f623f7b3f55,
0x3ef13dc93ec48000,0x3f223e953f0e3e48,0x3f753f463f6d3f35,0x3f7f3f623f7b3f55,0x3f623f7f3f6d3f80,0x3f463f753f553f7b,0x3e953f223ec43f35,0x3dc93ef13e483f0e,
0x3f313f733f463f7b,0x3efc3f583f183f67,0x3f7c3f4a3f753f35,0x3f7f3f6a3f803f5c,0xbf6fbf27bf62bf0e,0xbf7ebf51bf78bf3e,0xbe603e89bdc93ec4,0xbee63cc9beac3e16,
0xbf39bea1bf22be48,0xbf5fbf09bf4ebedb,0x3e2f3f1d3e953f35,0xbd973ecf3d493f04,0xbeb8bf42bef1bf55,0xbdfbbf13be79bf2c,0xbf7abf77bf7fbf6d,0xbf65bf80bf71bf7d,
0xbd49bf18be48bf35,0x3e79beac3dc9bef1,0x3f673f043f553ec4,0x3f7d3f3e3f753f22,0xbf2cbe16bf0e0000,0xbf5cbedbbf46be95,0xbf71bf78bf7bbf6d,0xbf4ebf80bf62bf7f,
0x3f803f4e3f7b3f35,0x3f783f713f7f3f62,0x3edb3f5c3f0e3f6d,0x3e163f2c3e953f46,0xbf3ebf7dbf55bf80,0xbf04bf67bf22bf75,0x3eacbe793e48bec4,0x3f183d493ef1bdc9,
0xbf5fbeb8bf46be48,0xbf7cbf27bf71bf04,0x3ea13f583ef13f6d,0xbcc93f1d3e163f3e,0x3f7e3f313f753f0e,0x3f7a3f653f803f4e,0x3d97bf13bdc9bf35,0x3ecfbe893e79bedb,
0xbefcbf6fbf22bf7b,0xbe2fbf42beacbf5c,0xbf73bf09bf62bec4,0xbf80bf4abf7dbf2c,0x3dfb3f393e953f55,0xbe603ee6bd493f18,0x3f7f3f513f7f3f35,0x3f6a3f773f783f67,
0x3f0e3f7b3f353f80,0x3e483f553ec43f6d,0xbf55be48bf350000,0xbf7bbf0ebf6dbec4,0xbf0ebf7bbf35bf80,0xbe48bf55bec4bf6d,0x3f553e483f350000,0x3f7b3f0e3f6d3ec4,
0xbf55be48bf358000,0xbf7bbf0ebf6dbec4,0xbf0ebf7bbf35bf80,0xbe48bf55bec4bf6d,0x3f553e483f358000,0x3f7b3f0e3f6d3ec4,0x3f0e3f7b3f353f80,0x3e483f553ec43f6d,
0x3efcbeb83e95bf0e,0x3f513d973f2cbe16,0xbf73bf58bf7fbf35,0xbf39bf7ebf5cbf71,0xbf4abcc9bf223e48,0xbf7abee6bf67be79,0x3f423f7c3f623f6d,0x3ecf3f773f183f80,
0x3f5f3f6f3f753f55,0x3f133f7f3f3e3f7d,0x3ea1bf093dc9bf35,0x3f31bdfb3f04beac,0xbf1dbf80bf46bf7b,0xbe60bf65bedbbf78,0xbf273e2fbef13ec4,0xbf6abe89bf4ebd49,
0xbf67bf5cbf7bbf35,0xbf18bf80bf46bf75,0x3f3ebe163f0ebec4,0x3f783eac3f623dc9,0x3f713e793f550000,0x3f7d3f2c3f7f3ef1,0xbd493f4e3e483f6d,0xbf043edbbe953f22,
0x3edbbf043e48bf35,0x3f4ebd493f22be95,0x3f2c3f7d3f553f6d,0x3e793f713ef13f7f,0x3eac3f783f0e3f80,0xbe163f3e3dc93f62,0xbf80bf18bf7bbec4,0xbf5cbf67bf75bf46,
0xbf313ea1bef13f0e,0xbf77be60bf5c3d49,0x3f7c3f1d3f7f3ec4,0x3f423f6f3f673f4e,0xbecfbf7fbf22bf7b,0x3dfbbf51be16bf71,0xbf093efcbe953f35,0xbf65bcc9bf3e3e79,
0xbf39bf73bf62bf55,0xbe89bf7abf04bf80,0xbe2f3f4a3dc93f6d,0xbf273eb8bedb3f18,0x3f6a3d973f46be48,0x3f7e3f133f7d3eac,0xbf58bf5fbf75bf35,0xbee6bf80bf2cbf78,
0xbdc9bf75bec4bf80,0x3ef1bf223e48bf55,0x3f463f623f6d3f35,0x3e953f7f3f0e3f7b,0xbf7fbe95bf6d0000,0xbf62bf46bf7bbf0e,0x3f22bef13ec4bf35,0x3f753dc93f55be48,
0x3f7f3e953f6d8000,0x3f623f463f7b3f0e,0xbf223ef1bec43f35,0xbf75bdc9bf553e48,0xbdc9bf75bec4bf80,0x3ef1bf223e48bf55,0x3f463f623f6d3f35,0x3e953f7f3f0e3f7b,
0xbf7abefcbf7fbe48,0xbf27bf6abf5cbf3e,0x3f313f653f623f35,0x3dfb3f7c3edb3f7d,0xbf133f1dbe953f55,0xbf733cc9bf4e3eac,0x3f6fbd973f46bec4,0x3f773f093f803e79,
0x3e60bf5fbdc9bf7b,0x3f42becf3f04bf2c,0xbf393ee6bef13f35,0xbf7ebe2fbf673e16,0xbf51bf4abf75bf0e,0xbea1bf80bf18bf71,0x3eb83f7f3f223f6d,0xbe893f583d493f78,
0xbf4e3edbbf0e3f35,0xbf80be79bf753dc9,0x3f04bf3e3e48bf6d,0x3f71be163f46bef1,0xbf7dbeacbf7b0000,0xbf2cbf5cbf62bf22,0x3f78bd493f55bec4,0x3f673f183f7f3e95,
0xbf18bf67bf55bf35,0x3d49bf78be95bf7f,0x3f5c3f2c3f7b3ec4,0x3eac3f7d3f223f62,0x3e16bf71be48bf80,0x3f3ebf043ef1bf46,0x3e793f803f0e3f6d,0xbedb3f4ebdc93f75,
0xbee63f58bdc93f7b,0xbf6f3e89bf3e3f18,0x3f1dbf393e95bf6d,0x3f7cbd973f5cbedb,0xbf423f13bef13f55,0xbf80bdfbbf713e79,0x3f5fbecf3f22bf35,0x3f7a3ea13f7dbd49,
0xbf65bf09bf7fbe48,0xbeb8bf77bf2cbf4e,0x3f4a3f313f753ec4,0x3e2f3f7f3f043f67,0xbf27bf51bf62bf0e,0x3cc9bf7ebeacbf78,0x3efc3f6a3f463f35,0xbe603f733e163f80,
0xbec43f6d00003f80,0xbf6d3ec4bf353f35,0x3ec4bf6d0000bf80,0x3f6dbec43f35bf35,0xbec43f6d00003f80,0xbf6d3ec4bf353f35,0x3ec4bf6d0000bf80,0x3f6dbec43f35bf35,
0xbf6dbec4bf808000,0xbec4bf6dbf35bf35,0x3f6d3ec43f808000,0x3ec43f6d3f353f35,0xbf6dbec4bf808000,0xbec4bf6dbf35bf35,0x3f6d3ec43f808000,0x3ec43f6d3f353f35,
0x3d973f7c3ef13f55,0xbf313f4abeac3f78,0xbe89bf6fbf22bf35,0x3f09bf653e16bf80,0xbea13f7a3dc93f7b,0xbf6a3efcbf2c3f4e,0x3dfbbf80be95bf6d,0x3f51bf273f04bf67,
0xbf7f3e2fbf623f0e,0xbf39bf1dbf71be79,0x3f77beb83f46bf35,0x3f583ee63f7d3d49,0xbf73be60bf7f3e48,0xbecfbf5fbf3ebf18,0x3f7e3cc93f75bec4,0x3f133f423f5c3edb,
0x3e163f713f0e3f35,0xbf2c3f5cbe953f7f,0x3e79bf80be48bf6d,0x3f67bf183f22bf62,0x3f4e3edb3f7b0000,0x3d493f783ef13f46,0xbf04bf3ebf55bec4,0x3eacbf7dbdc9bf75,
0xbf7d3eacbf553f35,0xbf3ebf04bf75bdc9,0x3f783d493f7bbec4,0x3edb3f4e3f463ef1,0xbf183f67be483f80,0xbf803e79bf623f22,0x3f5cbf2c3f0ebf6d,0x3f713e163f7fbe95,
0xbe2f3f7e3e953f55,0xbf653f31bf183f71,0xbecfbf42bf46bec4,0x3efcbf7a3d49bf78,0x3f583e893f7fbe48,0x3d973f6f3f043f2c,0xbf803ea1bf623f35,0xbf1dbf13bf67be16,
0xbf7c3dfbbf753f0e,0xbee6bf39bf4ebeac,0x3f6abf273f22bf6d,0x3f5f3e603f80be79,0xbf093f77bdc93f7b,0xbf7f3eb8bf5c3f3e,0xbcc9bf73bef1bf35,0x3f4abf513edbbf7d,
0x3f46bf623ec4bf80,0x3f75bdc93f7bbf0e,0xbf7f3e95bf6d3f35,0xbef1bf22bf55be48,0x3f223ef13f6d0000,0xbe953f7f3e483f55,0x3dc9bf75bec4bf35,0x3f62bf463f0ebf7b,
0x3f223ef13f6d8000,0xbe953f7f3e483f55,0x3dc9bf75bec4bf35,0x3f62bf463f0ebf7b,0xbf463f62bec43f80,0xbf753dc9bf7b3f0e,0x3f7fbe953f6dbf35,0x3ef13f223f553e48,
0x3f6fbf423f22bf7b,0x3f4a3e2f3f7dbeac,0xbe603f773e953f35,0xbf733f39bf2c3f78,0xbcc93f653ef13f0e,0xbf5f3f58bf043f80,0xbf51bdfbbf7f3ec4,0x3d97bf6abedbbf18,
0x3eb83f273f463e48,0xbf1d3f7cbe163f71,0xbf7a3e89bf753f35,0xbea1bf31bf3ebe79,0xbf803ee6bf623f55,0xbefcbf09bf5cbd49,0x3f13bf7e3dc9bf6d,0x3f7fbecf3f67bf4e,
0x3f71be793f7bbf35,0x3e163f3e3f223e95,0xbd49bf4ebf0ebec4,0x3f5cbf673ef1bf7f,0xbedbbf04bf550000,0x3f18bf803dc9bf62,0xbf2c3f7dbe483f6d,0xbf783eacbf753f46,
0xbeac3f783e483f35,0xbf7d3f2cbf463f75,0x3f80bf183f55bf6d,0x3f043edb3f62bdc9,0x3f67bf5c3f0ebf80,0x3f4e3d493f7fbef1,0xbf3ebe16bf7b3ec4,0x3e79bf71be95bf22,
0x3dfb3f313f223e48,0xbf583f73bedb3f78,0xbf7f3f13bf623f6d,0xbeb8befcbf4e3d49,0x3e89bf6abe95bf0e,0x3f7cbf423f3ebf7d,0x3f65be603f7fbf35,0xbcc93f4a3f043eac,
0xbf7e3f39bf463f7b,0xbf09bea1bf673e79,0x3d97bf51bef1bec4,0x3f6fbf5f3f18bf80,0x3f77becf3f75bf55,0x3e2f3f273f2c3e16,0xbee63f7a3dc93f35,0xbf803f1dbf5c3f71,
0xbf7b3f55bf353f80,0xbf0ebe48bf6d3ec4,0x3e483f0e3f350000,0xbf553f7bbec43f6d,0x3f7bbf553f35bf80,0x3f0e3e483f6dbec4,0xbe48bf0ebf350000,0x3f55bf7b3ec4bf6d,
0xbe48bf0ebf358000,0x3f55bf7b3ec4bf6d,0xbf7b3f55bf353f80,0xbf0ebe48bf6d3ec4,0x3e483f0e3f358000,0xbf553f7bbec43f6d,0x3f7bbf553f35bf80,0x3f0e3e483f6dbec4,
0xbf1dbcc9bf753f0e,0x3f09bf73bd49bf18,0x3f27bf7c3dc9bf35,0x3f6fbefc3f78bf67,0x3e893ecf3f46be48,0xbf513f7fbeac3f5c,0xbf653f7abef13f6d,0xbf393dfbbf7d3f2c,
0x3f4abf803e95bf55,0x3f58bea13f80bf4e,0x3f42be2f3f7fbf35,0xbeb83f5f3e793edb,0xbf773f6abf223f7b,0xbf13bd97bf713f04,0xbee6be60bf623ec4,0x3f31bf7e3e16bf3e,
0x3f3ebf7d3e48bf35,0x3f5cbedb3f7fbf62,0xbeacbe79bf553ec4,0x3f4ebf803e95bf46,0xbd493f183f0e0000,0xbf783f71bf223f75,0x3f67bf043f7bbf6d,0xbe163f2c3ef13dc9,
0x3f2cbe163f7bbf35,0xbf043f673dc93ef1,0x3f71bf783f0ebf6d,0x3f18bd493f75bf22,0xbf803f4ebf553f80,0xbe79beacbf463e95,0xbedb3f5c3e483ec4,0xbf7d3f3ebf623f7f,
0x3ecf3d973f62bf0e,0xbf4a3f7cbe793f2c,0xbf093f5f3dc93ec4,0xbf733f31bf713f7d,0xbf803f65bf463f7b,0xbe89be60bf4e3edb,0xbf133dfbbf753f35,0x3f27bf6f3d49bf04,
0xbf6a3f7fbef13f55,0xbf1d3e2fbf783f3e,0xbf583efcbf7f3f6d,0x3ea1bf39beacbe16,0xbcc9bee6bf223e48,0x3f77bf7a3f18bf67,0x3f51bf7e3e95bf35,0x3f42beb83f80bf5c,
0x3f75bf463f6dbf80,0xbdc93ef13f0ebe48,0x3f62bf7f3ec4bf35,0x3f22be953f7bbf55,0x3e95bf22bec40000,0x3f7fbf623f55bf7b,0xbef13dc9bf6d3f35,0x3f46bf753e48bf0e,
0xbe953f223ec48000,0xbf7f3f62bf553f7b,0x3ef1bdc93f6dbf35,0xbf463f75be483f0e,0x3f75bf463f6dbf80,0xbdc93ef13f0ebe48,0x3f62bf7f3ec4bf35,0x3f22be953f7bbf55,
0xbf133f4a3dc93e48,0xbf653f39bf783f80,0xbf6f3f7fbef13f35,0xbefc3e60bf713f4e,0x3f09be893f75bf55,0xbf423f6abe163edb,0xbcc93ea13f22bec4,0xbf7e3f7cbf2c3f5c,
0xbf513f1dbf7f3f7b,0x3ee6bf31be79bd49,0xbeb83d97bf623f35,0x3f5fbf7a3eacbf18,0xbf583f77be953f0e,0xbf273ecfbf7d3f67,0xbf803f73bf463f6d,0xbdfbbe2fbf3e3f04,
0xbe793d49bf553f35,0x3f71bf7d3ef1bf22,0xbf183edbbf7b3f6d,0x3f3ebf5c3dc9be95,0x3f04bf2cbe480000,0x3f67bf4e3f75bf7f,0x3e16beacbf0e3ec4,0x3f80bf783f46bf62,
0x3f78bf803f0ebf35,0x3eacbe163f62bf46,0x3f4ebf673e48bec4,0x3f2cbf043f7fbf75,0x3f5cbf3e3f7bbf80,0xbedb3f183e95bdc9,0x3f7dbf713f55bf6d,0xbd493e793f22bef1,
0x3f27bf133f7fbf7b,0xbf393f4abd493e16,0x3efcbecf3f75bf6d,0xbf583f65be793eac,0x3ea1be603f62bf55,0xbf6f3f77bedb3f04,0x3dfbbcc93f46bf35,0xbf7c3f7fbf183f2c,
0xbf423f51bdc93e48,0xbf313f1dbf803f7d,0xbf5f3f6abe953ec4,0xbf093ee6bf783f71,0xbf733f7abef13f0e,0xbeb83e89bf673f5c,0xbf7e3f80bf223f35,0xbe2f3d97bf4e3f3e,
0x3f003f003f003f00,0x3f003f003f003f00,0x3f003f003f003f00,0x3f003f003f003f00,0x3f003f003f003f00,0x3f003f003f003f00,0x3f003f003f003f00,0x3f003f003f003f00,
0xbf00bf003f003f00,0xbf00bf003f003f00,0xbf00bf003f003f00,0xbf00bf003f003f00,0xbf00bf003f003f00,0xbf00bf003f003f00,0xbf00bf003f003f00,0xbf00bf003f003f00,
0xbf73bf7abf75bf7b,0xbf6fbf77bf71bf78,0xbf7ebf80bf7fbf80,0xbf7cbf7fbf7dbf80,0xbf42bf51bf46bf55,0xbf39bf4abf3ebf4e,0xbf5fbf6abf62bf6d,0xbf58bf65bf5cbf67,
0x3ea13e603e953e48,0x3eb83e893eac3e79,0x3dfb3cc93dc98000,0x3e2f3d973e163d49,0x3f273f133f223f0e,0x3f313f1d3f2c3f18,0x3efc3ecf3ef13ec4,0x3f093ee63f043edb,
0x3f043f2c3f0e3f35,0x3edb3f183ef13f22,0x3e163eac3e483ec4,0x3d493e793dc93e95,0x3f783f803f7b3f80,0x3f713f7d3f753f7f,0x3f4e3f673f553f6d,0x3f3e3f5c3f463f62,
0xbf5cbf3ebf55bf35,0xbf67bf4ebf62bf46,0xbf7dbf71bf7bbf6d,0xbf80bf78bf7fbf75,0xbe79bd49be488000,0xbeacbe16be95bdc9,0xbf18bedbbf0ebec4,0xbf2cbf04bf22bef1,
0x3f093e893ef13e48,0x3f273ecf3f183eac,0xbcc9bea1bdc9bec4,0x3dfbbe2f3d49be79,0xbf13bf4abf22bf55,0xbee6bf31bf04bf3e,0xbf6fbf7fbf75bf80,0xbf5fbf7abf67bf7d,
0x3f583f773f623f7b,0x3f423f6a3f4e3f71,0x3f803f733f7f3f6d,0x3f7e3f7c3f803f78,0x3f513f1d3f463f0e,0x3f653f393f5c3f2c,0x3eb83d973e958000,0x3efc3e603edb3e16,
0x3f623f7f3f6d3f80,0x3f463f753f553f7b,0x3e953f223ec43f35,0x3dc93ef13e483f0e,0xbef1bdc9bec40000,0xbf22be95bf0ebe48,0xbf75bf46bf6dbf35,0xbf7fbf62bf7bbf55,
0xbef1bdc9bec48000,0xbf22be95bf0ebe48,0xbf75bf46bf6dbf35,0xbf7fbf62bf7bbf55,0xbf62bf7fbf6dbf80,0xbf46bf75bf55bf7b,0xbe95bf22bec4bf35,0xbdc9bef1be48bf0e,
0x3cc9bee6bdc9bf0e,0x3e89be603e16beac,0xbf51bf7ebf62bf80,0xbf27bf6fbf3ebf78,0x3f6a3f7f3f753f7b,0x3f4a3f7c3f5c3f80,0x3f583efc3f463ec4,0x3f733f313f673f18,
0x3f803f653f7f3f55,0x3f773f7a3f7d3f71,0x3f133dfb3ef18000,0x3f423eb83f2c3e79,0xbecf3d97be953e48,0xbf1dbe2fbf04bd49,0x3f093f5f3f223f6d,0x3ea13f393edb3f4e,
0xbf80bf4ebf7bbf35,0xbf78bf71bf7fbf62,0xbedbbf5cbf0ebf6d,0xbe16bf2cbe95bf46,0x3f3e3f7d3f553f80,0x3f043f673f223f75,0xbeac3e79be483ec4,0xbf18bd49bef13dc9,
0xbd49bf18be48bf35,0x3e79beac3dc9bef1,0x3f673f043f553ec4,0x3f7d3f3e3f753f22,0xbf2cbe16bf0e8000,0xbf5cbedbbf46be95,0xbf71bf78bf7bbf6d,0xbf4ebf80bf62bf7f,
0xbe893ecfbdc93f0e,0xbf133d97bedb3e79,0x3f653f7a3f753f6d,0x3f313f7e3f4e3f80,0x3f1dbcc93ef1be48,0x3f583ea13f3e3e16,0xbf27bf7cbf46bf80,0xbeb8bf5fbf04bf71,
0xbf77bf6abf7fbf55,0xbf51bf7fbf67bf78,0xbee63e60be953ec4,0xbf39bdfbbf183d49,0x3f4a3f803f623f7b,0x3f093f733f2c3f7d,0x3f423e2f3f228000,0x3f6f3efc3f5c3eac,
0x3f0e3f7b3f353f80,0x3e483f553ec43f6d,0xbf55be48bf350000,0xbf7bbf0ebf6dbec4,0xbf0ebf7bbf35bf80,0xbe48bf55bec4bf6d,0x3f553e483f350000,0x3f7b3f0e3f6d3ec4,
0xbf55be48bf358000,0xbf7bbf0ebf6dbec4,0xbf0ebf7bbf35bf80,0xbe48bf55bec4bf6d,0x3f553e483f358000,0x3f7b3f0e3f6d3ec4,0x3f0e3f7b3f353f80,0x3e483f553ec43f6d,
0x3f773ecf3f623e48,0x3f7c3f423f803f18,0xbee6bf7abf22bf80,0xbcc9bf4abe79bf67,0xbf7ebf39bf7fbf0e,0xbf58bf73bf71bf5c,0x3d973f513e953f6d,0xbeb83efcbe163f2c,
0x3e893f6a3ef13f7b,0xbe2f3f273d493f4e,0x3f653e603f468000,0x3f803f1d3f783edb,0x3dfbbf31bdc9bf55,0x3f09bea13eacbf04,0xbf7fbf13bf75bec4,0xbf6fbf5fbf7dbf3e,
0x3edbbf043e48bf35,0x3f4ebd493f22be95,0x3f2c3f7d3f553f6d,0x3e793f713ef13f7f,0x3eac3f783f0e3f80,0xbe163f3e3dc93f62,0xbf80bf18bf7bbec4,0xbf5cbf67bf75bf46,
0x3f673f5c3f7b3f35,0x3f183f803f463f75,0xbf3e3e16bf0e3ec4,0xbf78beacbf62bdc9,0xbf71be79bf558000,0xbf7dbf2cbf7fbef1,0x3d49bf4ebe48bf6d,0x3f04bedb3e95bf22,
0xbcc9bf65be95bf7b,0x3efcbf093e79bf3e,0xbf513dfbbf223ec4,0xbf7fbecfbf71be16,0x3f6f3f423f7f3f0e,0x3f1d3f7c3f4e3f67,0xbe60bf77bef1bf80,0x3ea1bf313d49bf5c,
0x3f803ee63f753e48,0x3f5f3f583f783f2c,0xbf13bf7ebf46bf6d,0xbd97bf6abeacbf7d,0xbeb83f27bdc93f55,0xbf4a3e2fbf183edb,0x3f7a3e893f628000,0x3f733f393f803f04,
0x3dc93f753ec43f80,0xbef13f22be483f55,0xbf46bf62bf6dbf35,0xbe95bf7fbf0ebf7b,0x3f7f3e953f6d0000,0x3f623f463f7b3f0e,0xbf223ef1bec43f35,0xbf75bdc9bf553e48,
0xbf7fbe95bf6d8000,0xbf62bf46bf7bbf0e,0x3f22bef13ec4bf35,0x3f753dc93f55be48,0x3dc93f753ec43f80,0xbef13f22be483f55,0xbf46bf62bf6dbf35,0xbe95bf7fbf0ebf7b,
0x3f093f773f463f55,0xbd973f6f3e793f80,0x3cc9bf73be95bf80,0x3f1dbf133eacbf4e,0x3f7c3dfb3f62be48,0x3f653f313f7d3edb,0xbf6abf27bf7fbec4,0xbefcbf7abf3ebf5c,
0xbf583e89bf223f0e,0xbf7fbeb8bf78bd49,0x3f803ea13f758000,0x3f4a3f513f713f18,0x3e2f3f7e3ef13f7b,0xbee63f39be163f67,0x3ecfbf423dc9bf6d,0x3f5fbe603f2cbf04,
0x3f183f673f553f35,0xbd493f783e953f7f,0xbf5cbf2cbf7bbec4,0xbeacbf7dbf22bf62,0xbe163f713e483f80,0xbf3e3f04bef13f46,0xbe79bf80bf0ebf6d,0x3edbbf4e3dc9bf75,
0xbf4e3edbbf0e3f35,0xbf80be79bf753dc9,0x3f04bf3e3e48bf6d,0x3f71be163f46bef1,0xbf7dbeacbf7b8000,0xbf2cbf5cbf62bf22,0x3f78bd493f55bec4,0x3f673f183f7f3e95,
0x3ea13f7a3f223f55,0xbecf3f5fbd493f7d,0xbdfbbf80bef1bf6d,0x3f13bf423e79bf71,0xbd973f7c3e953f7b,0xbf393f1dbedb3f5c,0x3e89bf6fbdc9bf80,0x3f58bee63f18bf3e,
0xbf733e60bf463f0e,0xbf6abefcbf80be16,0x3f7ebcc93f62bec4,0x3f513f273f783eac,0xbf7fbe2fbf753e48,0xbf31bf4abf67bf04,0x3f773eb83f7f8000,0x3f093f653f4e3f2c,
0xbec43f6d00003f80,0xbf6d3ec4bf353f35,0x3ec4bf6d0000bf80,0x3f6dbec43f35bf35,0xbec43f6d00003f80,0xbf6d3ec4bf353f35,0x3ec4bf6d0000bf80,0x3f6dbec43f35bf35,
0xbf6dbec4bf808000,0xbec4bf6dbf35bf35,0x3f6d3ec43f808000,0x3ec43f6d3f353f35,0xbf6dbec4bf808000,0xbec4bf6dbf35bf35,0x3f6d3ec43f808000,0x3ec43f6d3f353f35,
0xbf273f51be953f7b,0xbf803dfbbf673f04,0x3efcbf6a3dc9bf80,0x3f7abea13f4ebf2c,0xbf653f09bf223f55,0xbf6fbe89bf803e16,0x3f4abf313ef1bf6d,0x3f7c3d973f78beac,
0xbf42bf13bf75be48,0xbcc9bf7ebedbbf5c,0x3f5f3ecf3f7f8000,0x3e603f733f183f3e,0xbee6bf58bf46bf0e,0x3eb8bf77bd49bf7d,0x3f1d3f393f623ec4,0xbe2f3f7f3e793f71,
0xbf7d3eacbf553f35,0xbf3ebf04bf75bdc9,0x3f783d493f7bbec4,0x3edb3f4e3f463ef1,0xbf183f67be483f80,0xbf803e79bf623f22,0x3f5cbf2c3f0ebf6d,0x3f713e163f7fbe95,
0xbe16bf71bf0ebf35,0x3f2cbf5c3e95bf7f,0xbe793f803e483f6d,0xbf673f18bf223f62,0xbf4ebedbbf7b8000,0xbd49bf78bef1bf46,0x3f043f3e3f553ec4,0xbeac3f7d3dc93f75,
0xbf13bf1dbf62be48,0x3ea1bf80be16bf67,0x3f6f3d973f7fbec4,0x3e893f583f2c3f04,0xbf7a3efcbf463f55,0xbf42becfbf783d49,0x3f31bf653e95bf80,0x3f7ebe2f3f71bf18,
0x3f51bf4a3ef1bf7b,0x3f733cc93f7dbedb,0xbeb83f7f3dc93f6d,0xbf773f09bf3e3f5c,0xbe60bf5fbf22bf0e,0x3f27bf6a3e79bf80,0x3f393ee63f758000,0xbdfb3f7c3eac3f4e,
0xbf463f62bec43f80,0xbf753dc9bf7b3f0e,0x3f7fbe953f6dbf35,0x3ef13f223f553e48,0xbf22bef1bf6d0000,0x3e95bf7fbe48bf55,0xbdc93f753ec43f35,0xbf623f46bf0e3f7b,
0xbf22bef1bf6d8000,0x3e95bf7fbe48bf55,0xbdc93f753ec43f35,0xbf623f46bf0e3f7b,0x3f46bf623ec4bf80,0x3f75bdc93f7bbf0e,0xbf7f3e95bf6d3f35,0xbef1bf22bf55be48,
0xbf6a3d97bf7f3f0e,0xbdfbbf51bf18bedb,0x3f58bf5f3ef1bf80,0x3f65bcc93f80bf04,0x3f39bf733e95bf7b,0x3f77be603f78bf2c,0x3e2f3f4a3f223ec4,0xbf423f6fbeac3f7d,
0x3ecfbf7fbdc9bf55,0x3f7ebf133f4ebf67,0x3f093efc3f628000,0xbee63f803d493f5c,0x3f313ea13f75be48,0xbe893f7a3e793f3e,0xbf7c3f1dbf463f6d,0xbf27beb8bf713e16,
0x3eacbf78be48bf35,0x3f7dbf2c3f46bf75,0xbf803f18bf553f6d,0xbf04bedbbf623dc9,0xbf673f5cbf0e3f80,0xbf4ebd49bf7f3ef1,0x3f3e3e163f7bbec4,0xbe793f713e953f22,
0x3f71be793f7bbf35,0x3e163f3e3f223e95,0xbd49bf4ebf0ebec4,0x3f5cbf673ef1bf7f,0xbedbbf04bf558000,0x3f18bf803dc9bf62,0xbf2c3f7dbe483f6d,0xbf783eacbf753f46,
0x3f4abcc93f7fbf0e,0xbe603f653eac3f04,0xbf423f7cbe953f6d,0xbf6a3e89bf7d3f3e,0xbefcbeb8bf623e48,0x3f13bf7f3d49bf4e,0x3f73bf583f22bf80,0x3f313dfb3f78bedb,
0xbf1d3f80bdc93f55,0xbf7a3ee6bf713f5c,0xbf27be2fbf753ec4,0x3ecfbf77be16bf2c,0x3f5fbf6f3ef1bf7b,0x3f51bd973f80bf18,0x3ea13f093f468000,0xbf393f7ebe793f67,
0xbf7b3f55bf353f80,0xbf0ebe48bf6d3ec4,0x3e483f0e3f350000,0xbf553f7bbec43f6d,0x3f7bbf553f35bf80,0x3f0e3e483f6dbec4,0xbe48bf0ebf350000,0x3f55bf7b3ec4bf6d,
0xbe48bf0ebf358000,0x3f55bf7b3ec4bf6d,0xbf7b3f55bf353f80,0xbf0ebe48bf6d3ec4,0x3e483f0e3f358000,0xbf553f7bbec43f6d,0x3f7bbf553f35bf80,0x3f0e3e483f6dbec4,
0x3dfbbf39bef1be48,0x3f7abf653f2cbf7d,0x3f7fbf513f46bf80,0x3ecf3e893f5cbeac,0xbefc3f6f3dc93f0e,0xbf7c3f27bf673f78,0xbf733f09bf753f6d,0xbcc9bf1dbf18bd49,
0x3f7ebf313f62bf7b,0x3e603ee63f3ebe16,0x3d973f133f228000,0xbf6a3f77bf043f71,0xbf5f3eb8bf7f3f55,0x3e2fbf42bedbbe79,0x3ea1bf58be95bec4,0x3f80bf4a3f4ebf80,
0x3f2cbe163f7bbf35,0xbf043f673dc93ef1,0x3f71bf783f0ebf6d,0x3f18bd493f75bf22,0xbf803f4ebf553f80,0xbe79beacbf463e95,0xbedb3f5c3e483ec4,0xbf7d3f3ebf623f7f,
0xbf3e3f7dbe483f35,0xbf5c3edbbf7f3f62,0x3eac3e793f55bec4,0xbf4e3f80be953f46,0x3d49bf18bf0e8000,0x3f78bf713f22bf75,0xbf673f04bf7b3f6d,0x3e16bf2cbef1bdc9,
0xbf6f3f27bf753f7b,0x3dfbbf13bf043d49,0xbe60be89bf463ec4,0x3f65bf803edbbf4e,0x3f31bf733dc9bf0e,0x3f5fbf093f7dbf71,0x3f7cbf4a3f62bf80,0x3d973ecf3f2cbe79,
0x3eb8bf42be95be48,0x3f7ebf513f5cbf80,0x3f7abf773f22bf6d,0x3ee63cc93f67bf18,0x3f39bea13f7fbf55,0xbefc3f583e163eac,0xbe2f3f1d3ef18000,0xbf7f3f6abf3e3f78,
0xbf753f46bf6d3f80,0x3dc9bef1bf0e3e48,0xbf623f7fbec43f35,0xbf223e95bf7b3f55,0xbe953f223ec40000,0xbf7f3f62bf553f7b,0x3ef1bdc93f6dbf35,0xbf463f75be483f0e,
0x3e95bf22bec48000,0x3f7fbf623f55bf7b,0xbef13dc9bf6d3f35,0x3f46bf753e48bf0e,0xbf753f46bf6d3f80,0x3dc9bef1bf0e3e48,0xbf623f7fbec43f35,0xbf223e95bf7b3f55,
0x3f7cbf7e3f22bf55,0x3ea1bcc93f5cbf2c,0x3f6abf423f75bf80,0xbe893f093edbbe16,0x3e60befcbef13e48,0x3f7fbf6f3f4ebf71,0x3f39bf653dc9bec4,0x3f4abf133f80bf78,
0x3e2f3dfb3f46bf0e,0xbf733f80bf043f3e,0xbecf3f273e958000,0xbf773f58bf673f7d,0x3f7abf5f3f62bf7b,0xbd973eb83f18beac,0x3f31bee63f7fbf6d,0xbf1d3f513d493e79,
0xbf783f80bf0e3f35,0xbeac3e16bf623f46,0xbf4e3f67be483ec4,0xbf2c3f04bf7f3f75,0xbf5c3f3ebf7b3f80,0x3edbbf18be953dc9,0xbf7d3f71bf553f6d,0x3d49be79bf223ef1,
0xbe793d49bf553f35,0x3f71bf7d3ef1bf22,0xbf183edbbf7b3f6d,0x3f3ebf5c3dc9be95,0x3f04bf2cbe488000,0x3f67bf4e3f75bf7f,0x3e16beacbf0e3ec4,0x3f80bf783f46bf62,
0x3f7fbf7c3f46bf55,0xbcc93dfb3f2cbf18,0x3f77bf6f3f62bf6d,0xbe603ea13f04bedb,0x3f65bf583f75bf7b,0xbecf3efc3eacbe79,0x3f4abf393f7fbf80,0xbf133f273e16bd49,
0xbd973e2f3f22bf0e,0xbf803f7ebf3e3f4e,0xbe893eb83ef1bec4,0xbf7a3f73bf5c3f67,0xbee63f093e95be48,0xbf6a3f5fbf713f78,0xbf1d3f313dc98000,0xbf513f42bf7d3f80,
0x3f003f003f003f00,0x3f003f003f003f00,0x3f003f003f003f00,0x3f003f003f003f00,0x3f003f003f003f00,0x3f003f003f003f00,0x3f003f003f003f00,0x3f003f003f003f00,
0xbf00bf003f003f00,0xbf00bf003f003f00,0xbf00bf003f003f00,0xbf00bf003f003f00,0xbf00bf003f003f00,0xbf00bf003f003f00,0xbf00bf003f003f00,0xbf00bf003f003f00,
0xbee6bf09bef1bf0e,0xbecfbefcbedbbf04,0xbf1dbf31bf22bf35,0xbf13bf27bf18bf2c,0xbd97be2fbdc9be48,0xbcc9bdfbbd49be16,0xbe89beb8be95bec4,0xbe60bea1be79beac,
0x3f653f583f623f55,0x3f6a3f5f3f673f5c,0x3f4a3f393f463f35,0x3f513f423f4e3f3e,0x3f7f3f7c3f7f3f7b,0x3f803f7e3f803f7d,0x3f773f6f3f753f6d,0x3f7a3f733f783f71,
0xbf5cbf3ebf55bf35,0xbf67bf4ebf62bf46,0xbf7dbf71bf7bbf6d,0xbf80bf78bf7fbf75,0xbe79bd49be480000,0xbeacbe16be95bdc9,0xbf18bedbbf0ebec4,0xbf2cbf04bf22bef1,
0xbf04bf2cbf0ebf35,0xbedbbf18bef1bf22,0xbe16beacbe48bec4,0xbd49be79bdc9be95,0xbf78bf80bf7bbf80,0xbf71bf7dbf75bf7f,0xbf4ebf67bf55bf6d,0xbf3ebf5cbf46bf62,
0x3e603efc3e953f0e,0x3d973eb83e163edb,0x3f393f653f463f6d,0x3f1d3f513f2c3f5c,0x3f7c3f7e3f7f3f7b,0x3f733f803f783f80,0x3f6a3f423f623f35,0x3f773f583f713f4e,
0xbf7abf5fbf75bf55,0xbf7fbf6fbf7dbf67,0xbf31bee6bf22bec4,0xbf4abf13bf3ebf04,0xbe2f3dfbbdc93e48,0xbea1bcc9be793d49,0x3ecf3f273ef13f35,0x3e893f093eac3f18,
0xbf62bf7fbf6dbf80,0xbf46bf75bf55bf7b,0xbe95bf22bec4bf35,0xbdc9bef1be48bf0e,0x3ef13dc93ec40000,0x3f223e953f0e3e48,0x3f753f463f6d3f35,0x3f7f3f623f7b3f55,
0x3ef13dc93ec48000,0x3f223e953f0e3e48,0x3f753f463f6d3f35,0x3f7f3f623f7b3f55,0x3f623f7f3f6d3f80,0x3f463f753f553f7b,0x3e953f223ec43f35,0x3dc93ef13e483f0e,
0xbf39bea1bf22be48,0xbf5fbf09bf4ebedb,0x3e2f3f1d3e953f35,0xbd973ecf3d493f04,0xbeb8bf42bef1bf55,0xbdfbbf13be79bf2c,0xbf7abf77bf7fbf6d,0xbf65bf80bf71bf7d,
0xbf31bf73bf46bf7b,0xbefcbf58bf18bf67,0xbf7cbf4abf75bf35,0xbf7fbf6abf80bf5c,0x3f6f3f273f623f0e,0x3f7e3f513f783f3e,0x3e60be893dc9bec4,0x3ee6bcc93eacbe16,
0x3d493f183e483f35,0xbe793eacbdc93ef1,0xbf67bf04bf55bec4,0xbf7dbf3ebf75bf22,0x3f2c3e163f0e0000,0x3f5c3edb3f463e95,0x3f713f783f7b3f6d,0x3f4e3f803f623f7f,
0xbf80bf4ebf7bbf35,0xbf78bf71bf7fbf62,0xbedbbf5cbf0ebf6d,0xbe16bf2cbe95bf46,0x3f3e3f7d3f553f80,0x3f043f673f223f75,0xbeac3e79be483ec4,0xbf18bd49bef13dc9,
0x3efc3f6f3f223f7b,0x3e2f3f423eac3f5c,0x3f733f093f623ec4,0x3f803f4a3f7d3f2c,0xbdfbbf39be95bf55,0x3e60bee63d49bf18,0xbf7fbf51bf7fbf35,0xbf6abf77bf78bf67,
0xbf5fbeb8bf46be48,0xbf7cbf27bf71bf04,0x3ea13f583ef13f6d,0xbcc93f1d3e163f3e,0x3f7e3f313f753f0e,0x3f7a3f653f803f4e,0x3d97bf13bdc9bf35,0x3ecfbe893e79bedb,
0x3f0e3f7b3f353f80,0x3e483f553ec43f6d,0xbf55be48bf350000,0xbf7bbf0ebf6dbec4,0xbf0ebf7bbf35bf80,0xbe48bf55bec4bf6d,0x3f553e483f350000,0x3f7b3f0e3f6d3ec4,
0xbf55be48bf358000,0xbf7bbf0ebf6dbec4,0xbf0ebf7bbf35bf80,0xbe48bf55bec4bf6d,0x3f553e483f358000,0x3f7b3f0e3f6d3ec4,0x3f0e3f7b3f353f80,0x3e483f553ec43f6d,
0x3f5f3f6f3f753f55,0x3f133f7f3f3e3f7d,0x3ea1bf093dc9bf35,0x3f31bdfb3f04beac,0xbf1dbf80bf46bf7b,0xbe60bf65bedbbf78,0xbf273e2fbef13ec4,0xbf6abe89bf4ebd49,
0xbefc3eb8be953f0e,0xbf51bd97bf2c3e16,0x3f733f583f7f3f35,0x3f393f7e3f5c3f71,0x3f4a3cc93f22be48,0x3f7a3ee63f673e79,0xbf42bf7cbf62bf6d,0xbecfbf77bf18bf80,
0x3f673f5c3f7b3f35,0x3f183f803f463f75,0xbf3e3e16bf0e3ec4,0xbf78beacbf62bdc9,0xbf71be79bf550000,0xbf7dbf2cbf7fbef1,0x3d49bf4ebe48bf6d,0x3f04bedb3e95bf22,
0xbedb3f04be483f35,0xbf4e3d49bf223e95,0xbf2cbf7dbf55bf6d,0xbe79bf71bef1bf7f,0xbeacbf78bf0ebf80,0x3e16bf3ebdc9bf62,0x3f803f183f7b3ec4,0x3f5c3f673f753f46,
0x3f393f733f623f55,0x3e893f7a3f043f80,0x3e2fbf4abdc9bf6d,0x3f27beb83edbbf18,0xbf6abd97bf463e48,0xbf7ebf13bf7dbeac,0x3f583f5f3f753f35,0x3ee63f803f2c3f78,
0xbf313ea1bef13f0e,0xbf77be60bf5c3d49,0x3f7c3f1d3f7f3ec4,0x3f423f6f3f673f4e,0xbecfbf7fbf22bf7b,0x3dfbbf51be16bf71,0xbf093efcbe953f35,0xbf65bcc9bf3e3e79,
0xbdc9bf75bec4bf80,0x3ef1bf223e48bf55,0x3f463f623f6d3f35,0x3e953f7f3f0e3f7b,0xbf7fbe95bf6d0000,0xbf62bf46bf7bbf0e,0x3f22bef13ec4bf35,0x3f753dc93f55be48,
0x3f7f3e953f6d8000,0x3f623f463f7b3f0e,0xbf223ef1bec43f35,0xbf75bdc9bf553e48,0xbdc9bf75bec4bf80,0x3ef1bf223e48bf55,0x3f463f623f6d3f35,0x3e953f7f3f0e3f7b,
0x3e60bf5fbdc9bf7b,0x3f42becf3f04bf2c,0xbf393ee6bef13f35,0xbf7ebe2fbf673e16,0xbf51bf4abf75bf0e,0xbea1bf80bf18bf71,0x3eb83f7f3f223f6d,0xbe893f583d493f78,
0x3f7a3efc3f7f3e48,0x3f273f6a3f5c3f3e,0xbf31bf65bf62bf35,0xbdfbbf7cbedbbf7d,0x3f13bf1d3e95bf55,0x3f73bcc93f4ebeac,0xbf6f3d97bf463ec4,0xbf77bf09bf80be79,
0x3f4ebedb3f0ebf35,0x3f803e793f75bdc9,0xbf043f3ebe483f6d,0xbf713e16bf463ef1,0x3f7d3eac3f7b0000,0x3f2c3f5c3f623f22,0xbf783d49bf553ec4,0xbf67bf18bf7fbe95,
0x3f183f673f553f35,0xbd493f783e953f7f,0xbf5cbf2cbf7bbec4,0xbeacbf7dbf22bf62,0xbe163f713e483f80,0xbf3e3f04bef13f46,0xbe79bf80bf0ebf6d,0x3edbbf4e3dc9bf75,
0x3f653f093f7f3e48,0x3eb83f773f2c3f4e,0xbf4abf31bf75bec4,0xbe2fbf7fbf04bf67,0x3f273f513f623f0e,0xbcc93f7e3eac3f78,0xbefcbf6abf46bf35,0x3e60bf73be16bf80,
0xbee63f58bdc93f7b,0xbf6f3e89bf3e3f18,0x3f1dbf393e95bf6d,0x3f7cbd973f5cbedb,0xbf423f13bef13f55,0xbf80bdfbbf713e79,0x3f5fbecf3f22bf35,0x3f7a3ea13f7dbd49,
0xbec43f6d00003f80,0xbf6d3ec4bf353f35,0x3ec4bf6d0000bf80,0x3f6dbec43f35bf35,0xbec43f6d00003f80,0xbf6d3ec4bf353f35,0x3ec4bf6d0000bf80,0x3f6dbec43f35bf35,
0xbf6dbec4bf808000,0xbec4bf6dbf35bf35,0x3f6d3ec43f808000,0x3ec43f6d3f353f35,0xbf6dbec4bf808000,0xbec4bf6dbf35bf35,0x3f6d3ec43f808000,0x3ec43f6d3f353f35,
0xbf7f3e2fbf623f0e,0xbf39bf1dbf71be79,0x3f77beb83f46bf35,0x3f583ee63f7d3d49,0xbf73be60bf7f3e48,0xbecfbf5fbf3ebf18,0x3f7e3cc93f75bec4,0x3f133f423f5c3edb,
0xbd97bf7cbef1bf55,0x3f31bf4a3eacbf78,0x3e893f6f3f223f35,0xbf093f65be163f80,0x3ea1bf7abdc9bf7b,0x3f6abefc3f2cbf4e,0xbdfb3f803e953f6d,0xbf513f27bf043f67,
0xbe16bf71bf0ebf35,0x3f2cbf5c3e95bf7f,0xbe793f803e483f6d,0xbf673f18bf223f62,0xbf4ebedbbf7b0000,0xbd49bf78bef1bf46,0x3f043f3e3f553ec4,0xbeac3f7d3dc93f75,
0x3f7dbeac3f55bf35,0x3f3e3f043f753dc9,0xbf78bd49bf7b3ec4,0xbedbbf4ebf46bef1,0x3f18bf673e48bf80,0x3f80be793f62bf22,0xbf5c3f2cbf0e3f6d,0xbf71be16bf7f3e95,
0x3f7cbdfb3f75bf0e,0x3ee63f393f4e3eac,0xbf6a3f27bf223f6d,0xbf5fbe60bf803e79,0x3f09bf773dc9bf7b,0x3f7fbeb83f5cbf3e,0x3cc93f733ef13f35,0xbf4a3f51bedb3f7d,
0xbe2f3f7e3e953f55,0xbf653f31bf183f71,0xbecfbf42bf46bec4,0x3efcbf7a3d49bf78,0x3f583e893f7fbe48,0x3d973f6f3f043f2c,0xbf803ea1bf623f35,0xbf1dbf13bf67be16,
0x3f46bf623ec4bf80,0x3f75bdc93f7bbf0e,0xbf7f3e95bf6d3f35,0xbef1bf22bf55be48,0x3f223ef13f6d0000,0xbe953f7f3e483f55,0x3dc9bf75bec4bf35,0x3f62bf463f0ebf7b,
0x3f223ef13f6d8000,0xbe953f7f3e483f55,0x3dc9bf75bec4bf35,0x3f62bf463f0ebf7b,0xbf463f62bec43f80,0xbf753dc9bf7b3f0e,0x3f7fbe953f6dbf35,0x3ef13f223f553e48,
0x3eb83f273f463e48,0xbf1d3f7cbe163f71,0xbf7a3e89bf753f35,0xbea1bf31bf3ebe79,0xbf803ee6bf623f55,0xbefcbf09bf5cbd49,0x3f13bf7e3dc9bf6d,0x3f7fbecf3f67bf4e,
0xbf6f3f42bf223f7b,0xbf4abe2fbf7d3eac,0x3e60bf77be95bf35,0x3f73bf393f2cbf78,0x3cc9bf65bef1bf0e,0x3f5fbf583f04bf80,0x3f513dfb3f7fbec4,0xbd973f6a3edb3f18,
0xbf713e79bf7b3f35,0xbe16bf3ebf22be95,0x3d493f4e3f0e3ec4,0xbf5c3f67bef13f7f,0x3edb3f043f550000,0xbf183f80bdc93f62,0x3f2cbf7d3e48bf6d,0x3f78beac3f75bf46,
0x3eacbf78be48bf35,0x3f7dbf2c3f46bf75,0xbf803f18bf553f6d,0xbf04bedbbf623dc9,0xbf673f5cbf0e3f80,0xbf4ebd49bf7f3ef1,0x3f3e3e163f7bbec4,0xbe793f713e953f22,
0x3f7ebf393f46bf7b,0x3f093ea13f67be79,0xbd973f513ef13ec4,0xbf6f3f5fbf183f80,0xbf773ecfbf753f55,0xbe2fbf27bf2cbe16,0x3ee6bf7abdc9bf35,0x3f80bf1d3f5cbf71,
0x3dfb3f313f223e48,0xbf583f73bedb3f78,0xbf7f3f13bf623f6d,0xbeb8befcbf4e3d49,0x3e89bf6abe95bf0e,0x3f7cbf423f3ebf7d,0x3f65be603f7fbf35,0xbcc93f4a3f043eac,
0xbf7b3f55bf353f80,0xbf0ebe48bf6d3ec4,0x3e483f0e3f350000,0xbf553f7bbec43f6d,0x3f7bbf553f35bf80,0x3f0e3e483f6dbec4,0xbe48bf0ebf350000,0x3f55bf7b3ec4bf6d,
0xbe48bf0ebf358000,0x3f55bf7b3ec4bf6d,0xbf7b3f55bf353f80,0xbf0ebe48bf6d3ec4,0x3e483f0e3f358000,0xbf553f7bbec43f6d,0x3f7bbf553f35bf80,0x3f0e3e483f6dbec4,
0x3f4abf803e95bf55,0x3f58bea13f80bf4e,0x3f42be2f3f7fbf35,0xbeb83f5f3e793edb,0xbf773f6abf223f7b,0xbf13bd97bf713f04,0xbee6be60bf623ec4,0x3f31bf7e3e16bf3e,
0x3f1d3cc93f75bf0e,0xbf093f733d493f18,0xbf273f7cbdc93f35,0xbf6f3efcbf783f67,0xbe89becfbf463e48,0x3f51bf7f3eacbf5c,0x3f65bf7a3ef1bf6d,0x3f39bdfb3f7dbf2c,
0xbf3e3f7dbe483f35,0xbf5c3edbbf7f3f62,0x3eac3e793f55bec4,0xbf4e3f80be953f46,0x3d49bf18bf0e0000,0x3f78bf713f22bf75,0xbf673f04bf7b3f6d,0x3e16bf2cbef1bdc9,
0xbf2c3e16bf7b3f35,0x3f04bf67bdc9bef1,0xbf713f78bf0e3f6d,0xbf183d49bf753f22,0x3f80bf4e3f55bf80,0x3e793eac3f46be95,0x3edbbf5cbe48bec4,0x3f7dbf3e3f62bf7f,
0x3f6abf7f3ef1bf55,0x3f1dbe2f3f78bf3e,0x3f58befc3f7fbf6d,0xbea13f393eac3e16,0x3cc93ee63f22be48,0xbf773f7abf183f67,0xbf513f7ebe953f35,0xbf423eb8bf803f5c,
0x3ecf3d973f62bf0e,0xbf4a3f7cbe793f2c,0xbf093f5f3dc93ec4,0xbf733f31bf713f7d,0xbf803f65bf463f7b,0xbe89be60bf4e3edb,0xbf133dfbbf753f35,0x3f27bf6f3d49bf04,
0x3f75bf463f6dbf80,0xbdc93ef13f0ebe48,0x3f62bf7f3ec4bf35,0x3f22be953f7bbf55,0x3e95bf22bec40000,0x3f7fbf623f55bf7b,0xbef13dc9bf6d3f35,0x3f46bf753e48bf0e,
0xbe953f223ec48000,0xbf7f3f62bf553f7b,0x3ef1bdc93f6dbf35,0xbf463f75be483f0e,0x3f75bf463f6dbf80,0xbdc93ef13f0ebe48,0x3f62bf7f3ec4bf35,0x3f22be953f7bbf55,
0xbf513f1dbf7f3f7b,0x3ee6bf31be79bd49,0xbeb83d97bf623f35,0x3f5fbf7a3eacbf18,0xbf583f77be953f0e,0xbf273ecfbf7d3f67,0xbf803f73bf463f6d,0xbdfbbe2fbf3e3f04,
0x3f13bf4abdc9be48,0x3f65bf393f78bf80,0x3f6fbf7f3ef1bf35,0x3efcbe603f71bf4e,0xbf093e89bf753f55,0x3f42bf6a3e16bedb,0x3cc9bea1bf223ec4,0x3f7ebf7c3f2cbf5c,
0x3e79bd493f55bf35,0xbf713f7dbef13f22,0x3f18bedb3f7bbf6d,0xbf3e3f5cbdc93e95,0xbf043f2c3e480000,0xbf673f4ebf753f7f,0xbe163eac3f0ebec4,0xbf803f78bf463f62,
0xbf783f80bf0e3f35,0xbeac3e16bf623f46,0xbf4e3f67be483ec4,0xbf2c3f04bf7f3f75,0xbf5c3f3ebf7b3f80,0x3edbbf18be953dc9,0xbf7d3f71bf553f6d,0x3d49be79bf223ef1,
0x3f42bf513dc9be48,0x3f31bf1d3f80bf7d,0x3f5fbf6a3e95bec4,0x3f09bee63f78bf71,0x3f73bf7a3ef1bf0e,0x3eb8be893f67bf5c,0x3f7ebf803f22bf35,0x3e2fbd973f4ebf3e,
0x3f27bf133f7fbf7b,0xbf393f4abd493e16,0x3efcbecf3f75bf6d,0xbf583f65be793eac,0x3ea1be603f62bf55,0xbf6f3f77bedb3f04,0x3dfbbcc93f46bf35,0xbf7c3f7fbf183f2c,
0x3f003f003f003f00,0x3f003f003f003f00,0x3f003f003f003f00,0x3f003f003f003f00,0x3f003f003f003f00,0x3f003f003f003f00,0x3f003f003f003f00,0x3f003f003f003f00,
0xbf00bf003f003f00,0xbf00bf003f003f00,0xbf00bf003f003f00,0xbf00bf003f003f00,0xbf00bf003f003f00,0xbf00bf003f003f00,0xbf00bf003f003f00,0xbf00bf003f003f00,
0x3ea13e603e953e48,0x3eb83e893eac3e79,0x3dfb3cc93dc90000,0x3e2f3d973e163d49,0x3f273f133f223f0e,0x3f313f1d3f2c3f18,0x3efc3ecf3ef13ec4,0x3f093ee63f043edb,
0x3f733f7a3f753f7b,0x3f6f3f773f713f78,0x3f7e3f803f7f3f80,0x3f7c3f7f3f7d3f80,0x3f423f513f463f55,0x3f393f4a3f3e3f4e,0x3f5f3f6a3f623f6d,0x3f583f653f5c3f67,
0xbf04bf2cbf0ebf35,0xbedbbf18bef1bf22,0xbe16beacbe48bec4,0xbd49be79bdc9be95,0xbf78bf80bf7bbf80,0xbf71bf7dbf75bf7f,0xbf4ebf67bf55bf6d,0xbf3ebf5cbf46bf62,
0x3f5c3f3e3f553f35,0x3f673f4e3f623f46,0x3f7d3f713f7b3f6d,0x3f803f783f7f3f75,0x3e793d493e488000,0x3eac3e163e953dc9,0x3f183edb3f0e3ec4,0x3f2c3f043f223ef1,
0xbf58bf77bf62bf7b,0xbf42bf6abf4ebf71,0xbf80bf73bf7fbf6d,0xbf7ebf7cbf80bf78,0xbf51bf1dbf46bf0e,0xbf65bf39bf5cbf2c,0xbeb8bd97be950000,0xbefcbe60bedbbe16,
0x3f093e893ef13e48,0x3f273ecf3f183eac,0xbcc9bea1bdc9bec4,0x3dfbbe2f3d49be79,0xbf13bf4abf22bf55,0xbee6bf31bf04bf3e,0xbf6fbf7fbf75bf80,0xbf5fbf7abf67bf7d,
0x3f623f7f3f6d3f80,0x3f463f753f553f7b,0x3e953f223ec43f35,0x3dc93ef13e483f0e,0xbef1bdc9bec40000,0xbf22be95bf0ebe48,0xbf75bf46bf6dbf35,0xbf7fbf62bf7bbf55,
0xbef1bdc9bec48000,0xbf22be95bf0ebe48,0xbf75bf46bf6dbf35,0xbf7fbf62bf7bbf55,0xbf62bf7fbf6dbf80,0xbf46bf75bf55bf7b,0xbe95bf22bec4bf35,0xbdc9bef1be48bf0e,
0x3f803f653f7f3f55,0x3f773f7a3f7d3f71,0x3f133dfb3ef10000,0x3f423eb83f2c3e79,0xbecf3d97be953e48,0xbf1dbe2fbf04bd49,0x3f093f5f3f223f6d,0x3ea13f393edb3f4e,
0xbcc93ee63dc93f0e,0xbe893e60be163eac,0x3f513f7e3f623f80,0x3f273f6f3f3e3f78,0xbf6abf7fbf75bf7b,0xbf4abf7cbf5cbf80,0xbf58befcbf46bec4,0xbf73bf31bf67bf18,
0x3f803f4e3f7b3f35,0x3f783f713f7f3f62,0x3edb3f5c3f0e3f6d,0x3e163f2c3e953f46,0xbf3ebf7dbf55bf80,0xbf04bf67bf22bf75,0x3eacbe793e48bec4,0x3f183d493ef1bdc9,
0x3d493f183e483f35,0xbe793eacbdc93ef1,0xbf67bf04bf55bec4,0xbf7dbf3ebf75bf22,0x3f2c3e163f0e8000,0x3f5c3edb3f463e95,0x3f713f783f7b3f6d,0x3f4e3f803f623f7f,
0x3f773f6a3f7f3f55,0x3f513f7f3f673f78,0x3ee6be603e95bec4,0x3f393dfb3f18bd49,0xbf4abf80bf62bf7b,0xbf09bf73bf2cbf7d,0xbf42be2fbf220000,0xbf6fbefcbf5cbeac,
0xbe893ecfbdc93f0e,0xbf133d97bedb3e79,0x3f653f7a3f753f6d,0x3f313f7e3f4e3f80,0x3f1dbcc93ef1be48,0x3f583ea13f3e3e16,0xbf27bf7cbf46bf80,0xbeb8bf5fbf04bf71,
0x3f0e3f7b3f353f80,0x3e483f553ec43f6d,0xbf55be48bf350000,0xbf7bbf0ebf6dbec4,0xbf0ebf7bbf35bf80,0xbe48bf55bec4bf6d,0x3f553e483f350000,0x3f7b3f0e3f6d3ec4,
0xbf55be48bf358000,0xbf7bbf0ebf6dbec4,0xbf0ebf7bbf35bf80,0xbe48bf55bec4bf6d,0x3f553e483f358000,0x3f7b3f0e3f6d3ec4,0x3f0e3f7b3f353f80,0x3e483f553ec43f6d,
0x3e893f6a3ef13f7b,0xbe2f3f273d493f4e,0x3f653e603f460000,0x3f803f1d3f783edb,0x3dfbbf31bdc9bf55,0x3f09bea13eacbf04,0xbf7fbf13bf75bec4,0xbf6fbf5fbf7dbf3e,
0xbf77becfbf62be48,0xbf7cbf42bf80bf18,0x3ee63f7a3f223f80,0x3cc93f4a3e793f67,0x3f7e3f393f7f3f0e,0x3f583f733f713f5c,0xbd97bf51be95bf6d,0x3eb8befc3e16bf2c,
0xbedb3f04be483f35,0xbf4e3d49bf223e95,0xbf2cbf7dbf55bf6d,0xbe79bf71bef1bf7f,0xbeacbf78bf0ebf80,0x3e16bf3ebdc9bf62,0x3f803f183f7b3ec4,0x3f5c3f673f753f46,
0xbf67bf5cbf7bbf35,0xbf18bf80bf46bf75,0x3f3ebe163f0ebec4,0x3f783eac3f623dc9,0x3f713e793f558000,0x3f7d3f2c3f7f3ef1,0xbd493f4e3e483f6d,0xbf043edbbe953f22,
0xbf80bee6bf75be48,0xbf5fbf58bf78bf2c,0x3f133f7e3f463f6d,0x3d973f6a3eac3f7d,0x3eb8bf273dc9bf55,0x3f4abe2f3f18bedb,0xbf7abe89bf620000,0xbf73bf39bf80bf04,
0xbcc9bf65be95bf7b,0x3efcbf093e79bf3e,0xbf513dfbbf223ec4,0xbf7fbecfbf71be16,0x3f6f3f423f7f3f0e,0x3f1d3f7c3f4e3f67,0xbe60bf77bef1bf80,0x3ea1bf313d49bf5c,
0x3dc93f753ec43f80,0xbef13f22be483f55,0xbf46bf62bf6dbf35,0xbe95bf7fbf0ebf7b,0x3f7f3e953f6d0000,0x3f623f463f7b3f0e,0xbf223ef1bec43f35,0xbf75bdc9bf553e48,
0xbf7fbe95bf6d8000,0xbf62bf46bf7bbf0e,0x3f22bef13ec4bf35,0x3f753dc93f55be48,0x3dc93f753ec43f80,0xbef13f22be483f55,0xbf46bf62bf6dbf35,0xbe95bf7fbf0ebf7b,
0xbf583e89bf223f0e,0xbf7fbeb8bf78bd49,0x3f803ea13f750000,0x3f4a3f513f713f18,0x3e2f3f7e3ef13f7b,0xbee63f39be163f67,0x3ecfbf423dc9bf6d,0x3f5fbe603f2cbf04,
0xbf09bf77bf46bf55,0x3d97bf6fbe79bf80,0xbcc93f733e953f80,0xbf1d3f13beac3f4e,0xbf7cbdfbbf623e48,0xbf65bf31bf7dbedb,0x3f6a3f273f7f3ec4,0x3efc3f7a3f3e3f5c,
0xbf18bf67bf55bf35,0x3d49bf78be95bf7f,0x3f5c3f2c3f7b3ec4,0x3eac3f7d3f223f62,0x3e16bf71be48bf80,0x3f3ebf043ef1bf46,0x3e793f803f0e3f6d,0xbedb3f4ebdc93f75,
0x3f4ebedb3f0ebf35,0x3f803e793f75bdc9,0xbf043f3ebe483f6d,0xbf713e16bf463ef1,0x3f7d3eac3f7b8000,0x3f2c3f5c3f623f22,0xbf783d49bf553ec4,0xbf67bf18bf7fbe95,
0x3f73be603f46bf0e,0x3f6a3efc3f803e16,0xbf7e3cc9bf623ec4,0xbf51bf27bf78beac,0x3f7f3e2f3f75be48,0x3f313f4a3f673f04,0xbf77beb8bf7f0000,0xbf09bf65bf4ebf2c,
0x3ea13f7a3f223f55,0xbecf3f5fbd493f7d,0xbdfbbf80bef1bf6d,0x3f13bf423e79bf71,0xbd973f7c3e953f7b,0xbf393f1dbedb3f5c,0x3e89bf6fbdc9bf80,0x3f58bee63f18bf3e,
0xbec43f6d00003f80,0xbf6d3ec4bf353f35,0x3ec4bf6d0000bf80,0x3f6dbec43f35bf35,0xbec43f6d00003f80,0xbf6d3ec4bf353f35,0x3ec4bf6d0000bf80,0x3f6dbec43f35bf35,
0xbf6dbec4bf808000,0xbec4bf6dbf35bf35,0x3f6d3ec43f808000,0x3ec43f6d3f353f35,0xbf6dbec4bf808000,0xbec4bf6dbf35bf35,0x3f6d3ec43f808000,0x3ec43f6d3f353f35,
0xbf42bf13bf75be48,0xbcc9bf7ebedbbf5c,0x3f5f3ecf3f7f0000,0x3e603f733f183f3e,0xbee6bf58bf46bf0e,0x3eb8bf77bd49bf7d,0x3f1d3f393f623ec4,0xbe2f3f7f3e793f71,
0x3f27bf513e95bf7b,0x3f80bdfb3f67bf04,0xbefc3f6abdc93f80,0xbf7a3ea1bf4e3f2c,0x3f65bf093f22bf55,0x3f6f3e893f80be16,0xbf4a3f31bef13f6d,0xbf7cbd97bf783eac,
0x3f7dbeac3f55bf35,0x3f3e3f043f753dc9,0xbf78bd49bf7b3ec4,0xbedbbf4ebf46bef1,0x3f18bf673e48bf80,0x3f80be793f62bf22,0xbf5c3f2cbf0e3f6d,0xbf71be16bf7f3e95,
0x3e163f713f0e3f35,0xbf2c3f5cbe953f7f,0x3e79bf80be48bf6d,0x3f67bf183f22bf62,0x3f4e3edb3f7b8000,0x3d493f783ef13f46,0xbf04bf3ebf55bec4,0x3eacbf7dbdc9bf75,
0xbf513f4abef13f7b,0xbf73bcc9bf7d3edb,0x3eb8bf7fbdc9bf6d,0x3f77bf093f3ebf5c,0x3e603f5f3f223f0e,0xbf273f6abe793f80,0xbf39bee6bf750000,0x3dfbbf7cbeacbf4e,
0xbf13bf1dbf62be48,0x3ea1bf80be16bf67,0x3f6f3d973f7fbec4,0x3e893f583f2c3f04,0xbf7a3efcbf463f55,0xbf42becfbf783d49,0x3f31bf653e95bf80,0x3f7ebe2f3f71bf18,
0xbf463f62bec43f80,0xbf753dc9bf7b3f0e,0x3f7fbe953f6dbf35,0x3ef13f223f553e48,0xbf22bef1bf6d0000,0x3e95bf7fbe48bf55,0xbdc93f753ec43f35,0xbf623f46bf0e3f7b,
0xbf22bef1bf6d8000,0x3e95bf7fbe48bf55,0xbdc93f753ec43f35,0xbf623f46bf0e3f7b,0x3f46bf623ec4bf80,0x3f75bdc93f7bbf0e,0xbf7f3e95bf6d3f35,0xbef1bf22bf55be48,
0x3ecfbf7fbdc9bf55,0x3f7ebf133f4ebf67,0x3f093efc3f620000,0xbee63f803d493f5c,0x3f313ea13f75be48,0xbe893f7a3e793f3e,0xbf7c3f1dbf463f6d,0xbf27beb8bf713e16,
0x3f6abd973f7fbf0e,0x3dfb3f513f183edb,0xbf583f5fbef13f80,0xbf653cc9bf803f04,0xbf393f73be953f7b,0xbf773e60bf783f2c,0xbe2fbf4abf22bec4,0x3f42bf6f3eacbf7d,
0xbeac3f783e483f35,0xbf7d3f2cbf463f75,0x3f80bf183f55bf6d,0x3f043edb3f62bdc9,0x3f67bf5c3f0ebf80,0x3f4e3d493f7fbef1,0xbf3ebe16bf7b3ec4,0x3e79bf71be95bf22,
0xbf713e79bf7b3f35,0xbe16bf3ebf22be95,0x3d493f4e3f0e3ec4,0xbf5c3f67bef13f7f,0x3edb3f043f558000,0xbf183f80bdc93f62,0x3f2cbf7d3e48bf6d,0x3f78beac3f75bf46,
0x3f1dbf803dc9bf55,0x3f7abee63f71bf5c,0x3f273e2f3f75bec4,0xbecf3f773e163f2c,0xbf5f3f6fbef13f7b,0xbf513d97bf803f18,0xbea1bf09bf460000,0x3f39bf7e3e79bf67,
0x3f4abcc93f7fbf0e,0xbe603f653eac3f04,0xbf423f7cbe953f6d,0xbf6a3e89bf7d3f3e,0xbefcbeb8bf623e48,0x3f13bf7f3d49bf4e,0x3f73bf583f22bf80,0x3f313dfb3f78bedb,
0xbf7b3f55bf353f80,0xbf0ebe48bf6d3ec4,0x3e483f0e3f350000,0xbf553f7bbec43f6d,0x3f7bbf553f35bf80,0x3f0e3e483f6dbec4,0xbe48bf0ebf350000,0x3f55bf7b3ec4bf6d,
0xbe48bf0ebf358000,0x3f55bf7b3ec4bf6d,0xbf7b3f55bf353f80,0xbf0ebe48bf6d3ec4,0x3e483f0e3f358000,0xbf553f7bbec43f6d,0x3f7bbf553f35bf80,0x3f0e3e483f6dbec4,
0x3f7ebf313f62bf7b,0x3e603ee63f3ebe16,0x3d973f133f220000,0xbf6a3f77bf043f71,0xbf5f3eb8bf7f3f55,0x3e2fbf42bedbbe79,0x3ea1bf58be95bec4,0x3f80bf4a3f4ebf80,
0xbdfb3f393ef13e48,0xbf7a3f65bf2c3f7d,0xbf7f3f51bf463f80,0xbecfbe89bf5c3eac,0x3efcbf6fbdc9bf0e,0x3f7cbf273f67bf78,0x3f73bf093f75bf6d,0x3cc93f1d3f183d49,
0xbf2c3e16bf7b3f35,0x3f04bf67bdc9bef1,0xbf713f78bf0e3f6d,0xbf183d49bf753f22,0x3f80bf4e3f55bf80,0x3e793eac3f46be95,0x3edbbf5cbe48bec4,0x3f7dbf3e3f62bf7f,
0x3f3ebf7d3e48bf35,0x3f5cbedb3f7fbf62,0xbeacbe79bf553ec4,0x3f4ebf803e95bf46,0xbd493f183f0e8000,0xbf783f71bf223f75,0x3f67bf043f7bbf6d,0xbe163f2c3ef13dc9,
0xbeb83f423e953e48,0xbf7e3f51bf5c3f80,0xbf7a3f77bf223f6d,0xbee6bcc9bf673f18,0xbf393ea1bf7f3f55,0x3efcbf58be16beac,0x3e2fbf1dbef10000,0x3f7fbf6a3f3ebf78,
0xbf6f3f27bf753f7b,0x3dfbbf13bf043d49,0xbe60be89bf463ec4,0x3f65bf803edbbf4e,0x3f31bf733dc9bf0e,0x3f5fbf093f7dbf71,0x3f7cbf4a3f62bf80,0x3d973ecf3f2cbe79,
0xbf753f46bf6d3f80,0x3dc9bef1bf0e3e48,0xbf623f7fbec43f35,0xbf223e95bf7b3f55,0xbe953f223ec40000,0xbf7f3f62bf553f7b,0x3ef1bdc93f6dbf35,0xbf463f75be483f0e,
0x3e95bf22bec48000,0x3f7fbf623f55bf7b,0xbef13dc9bf6d3f35,0x3f46bf753e48bf0e,0xbf753f46bf6d3f80,0x3dc9bef1bf0e3e48,0xbf623f7fbec43f35,0xbf223e95bf7b3f55,
0x3e2f3dfb3f46bf0e,0xbf733f80bf043f3e,0xbecf3f273e950000,0xbf773f58bf673f7d,0x3f7abf5f3f62bf7b,0xbd973eb83f18beac,0x3f31bee63f7fbf6d,0xbf1d3f513d493e79,
0xbf7c3f7ebf223f55,0xbea13cc9bf5c3f2c,0xbf6a3f42bf753f80,0x3e89bf09bedb3e16,0xbe603efc3ef1be48,0xbf7f3f6fbf4e3f71,0xbf393f65bdc93ec4,0xbf4a3f13bf803f78,
0x3f78bf803f0ebf35,0x3eacbe163f62bf46,0x3f4ebf673e48bec4,0x3f2cbf043f7fbf75,0x3f5cbf3e3f7bbf80,0xbedb3f183e95bdc9,0x3f7dbf713f55bf6d,0xbd493e793f22bef1,
0x3e79bd493f55bf35,0xbf713f7dbef13f22,0x3f18bedb3f7bbf6d,0xbf3e3f5cbdc93e95,0xbf043f2c3e488000,0xbf673f4ebf753f7f,0xbe163eac3f0ebec4,0xbf803f78bf463f62,
0x3d97be2fbf223f0e,0x3f80bf7e3f3ebf4e,0x3e89beb8bef13ec4,0x3f7abf733f5cbf67,0x3ee6bf09be953e48,0x3f6abf5f3f71bf78,0x3f1dbf31bdc90000,0x3f51bf423f7dbf80,
0x3f7fbf7c3f46bf55,0xbcc93dfb3f2cbf18,0x3f77bf6f3f62bf6d,0xbe603ea13f04bedb,0x3f65bf583f75bf7b,0xbecf3efc3eacbe79,0x3f4abf393f7fbf80,0xbf133f273e16bd49,
0x3f003f003f003f00,0x3f003f003f003f00,0x3f003f003f003f00,0x3f003f003f003f00,0x3f003f003f003f00,0x3f003f003f003f00,0x3f003f003f003f00,0x3f003f003f003f00,
0xbf00bf003f003f00,0xbf00bf003f003f00,0xbf00bf003f003f00,0xbf00bf003f003f00,0xbf00bf003f003f00,0xbf00bf003f003f00,0xbf00bf003f003f00,0xbf00bf003f003f00,
0x3f653f583f623f55,0x3f6a3f5f3f673f5c,0x3f4a3f393f463f35,0x3f513f423f4e3f3e,0x3f7f3f7c3f7f3f7b,0x3f803f7e3f803f7d,0x3f773f6f3f753f6d,0x3f7a3f733f783f71,
0x3ee63f093ef13f0e,0x3ecf3efc3edb3f04,0x3f1d3f313f223f35,0x3f133f273f183f2c,0x3d973e2f3dc93e48,0x3cc93dfb3d493e16,0x3e893eb83e953ec4,0x3e603ea13e793eac,
0x3f5c3f3e3f553f35,0x3f673f4e3f623f46,0x3f7d3f713f7b3f6d,0x3f803f783f7f3f75,0x3e793d493e480000,0x3eac3e163e953dc9,0x3f183edb3f0e3ec4,0x3f2c3f043f223ef1,
0x3f043f2c3f0e3f35,0x3edb3f183ef13f22,0x3e163eac3e483ec4,0x3d493e793dc93e95,0x3f783f803f7b3f80,0x3f713f7d3f753f7f,0x3f4e3f673f553f6d,0x3f3e3f5c3f463f62,
0x3f7a3f5f3f753f55,0x3f7f3f6f3f7d3f67,0x3f313ee63f223ec4,0x3f4a3f133f3e3f04,0x3e2fbdfb3dc9be48,0x3ea13cc93e79bd49,0xbecfbf27bef1bf35,0xbe89bf09beacbf18,
0x3e603efc3e953f0e,0x3d973eb83e163edb,0x3f393f653f463f6d,0x3f1d3f513f2c3f5c,0x3f7c3f7e3f7f3f7b,0x3f733f803f783f80,0x3f6a3f423f623f35,0x3f773f583f713f4e,
0xbf62bf7fbf6dbf80,0xbf46bf75bf55bf7b,0xbe95bf22bec4bf35,0xbdc9bef1be48bf0e,0x3ef13dc93ec40000,0x3f223e953f0e3e48,0x3f753f463f6d3f35,0x3f7f3f623f7b3f55,
0x3ef13dc93ec48000,0x3f223e953f0e3e48,0x3f753f463f6d3f35,0x3f7f3f623f7b3f55,0x3f623f7f3f6d3f80,0x3f463f753f553f7b,0x3e953f223ec43f35,0x3dc93ef13e483f0e,
0xbf31bf73bf46bf7b,0xbefcbf58bf18bf67,0xbf7cbf4abf75bf35,0xbf7fbf6abf80bf5c,0x3f6f3f273f623f0e,0x3f7e3f513f783f3e,0x3e60be893dc9bec4,0x3ee6bcc93eacbe16,
0x3f393ea13f223e48,0x3f5f3f093f4e3edb,0xbe2fbf1dbe95bf35,0x3d97becfbd49bf04,0x3eb83f423ef13f55,0x3dfb3f133e793f2c,0x3f7a3f773f7f3f6d,0x3f653f803f713f7d,
0xbd49bf18be48bf35,0x3e79beac3dc9bef1,0x3f673f043f553ec4,0x3f7d3f3e3f753f22,0xbf2cbe16bf0e0000,0xbf5cbedbbf46be95,0xbf71bf78bf7bbf6d,0xbf4ebf80bf62bf7f,
0x3f803f4e3f7b3f35,0x3f783f713f7f3f62,0x3edb3f5c3f0e3f6d,0x3e163f2c3e953f46,0xbf3ebf7dbf55bf80,0xbf04bf67bf22bf75,0x3eacbe793e48bec4,0x3f183d493ef1bdc9,
0x3f5f3eb83f463e48,0x3f7c3f273f713f04,0xbea1bf58bef1bf6d,0x3cc9bf1dbe16bf3e,0xbf7ebf31bf75bf0e,0xbf7abf65bf80bf4e,0xbd973f133dc93f35,0xbecf3e89be793edb,
0x3efc3f6f3f223f7b,0x3e2f3f423eac3f5c,0x3f733f093f623ec4,0x3f803f4a3f7d3f2c,0xbdfbbf39be95bf55,0x3e60bee63d49bf18,0xbf7fbf51bf7fbf35,0xbf6abf77bf78bf67,
0x3f0e3f7b3f353f80,0x3e483f553ec43f6d,0xbf55be48bf350000,0xbf7bbf0ebf6dbec4,0xbf0ebf7bbf35bf80,0xbe48bf55bec4bf6d,0x3f553e483f350000,0x3f7b3f0e3f6d3ec4,
0xbf55be48bf358000,0xbf7bbf0ebf6dbec4,0xbf0ebf7bbf35bf80,0xbe48bf55bec4bf6d,0x3f553e483f358000,0x3f7b3f0e3f6d3ec4,0x3f0e3f7b3f353f80,0x3e483f553ec43f6d,
0xbefc3eb8be953f0e,0xbf51bd97bf2c3e16,0x3f733f583f7f3f35,0x3f393f7e3f5c3f71,0x3f4a3cc93f22be48,0x3f7a3ee63f673e79,0xbf42bf7cbf62bf6d,0xbecfbf77bf18bf80,
0xbf5fbf6fbf75bf55,0xbf13bf7fbf3ebf7d,0xbea13f09bdc93f35,0xbf313dfbbf043eac,0x3f1d3f803f463f7b,0x3e603f653edb3f78,0x3f27be2f3ef1bec4,0x3f6a3e893f4e3d49,
0xbf67bf5cbf7bbf35,0xbf18bf80bf46bf75,0x3f3ebe163f0ebec4,0x3f783eac3f623dc9,0x3f713e793f550000,0x3f7d3f2c3f7f3ef1,0xbd493f4e3e483f6d,0xbf043edbbe953f22,
0x3edbbf043e48bf35,0x3f4ebd493f22be95,0x3f2c3f7d3f553f6d,0x3e793f713ef13f7f,0x3eac3f783f0e3f80,0xbe163f3e3dc93f62,0xbf80bf18bf7bbec4,0xbf5cbf67bf75bf46,
0x3f31bea13ef1bf0e,0x3f773e603f5cbd49,0xbf7cbf1dbf7fbec4,0xbf42bf6fbf67bf4e,0x3ecf3f7f3f223f7b,0xbdfb3f513e163f71,0x3f09befc3e95bf35,0x3f653cc93f3ebe79,
0x3f393f733f623f55,0x3e893f7a3f043f80,0x3e2fbf4abdc9bf6d,0x3f27beb83edbbf18,0xbf6abd97bf463e48,0xbf7ebf13bf7dbeac,0x3f583f5f3f753f35,0x3ee63f803f2c3f78,
0xbdc9bf75bec4bf80,0x3ef1bf223e48bf55,0x3f463f623f6d3f35,0x3e953f7f3f0e3f7b,0xbf7fbe95bf6d0000,0xbf62bf46bf7bbf0e,0x3f22bef13ec4bf35,0x3f753dc93f55be48,
0x3f7f3e953f6d8000,0x3f623f463f7b3f0e,0xbf223ef1bec43f35,0xbf75bdc9bf553e48,0xbdc9bf75bec4bf80,0x3ef1bf223e48bf55,0x3f463f623f6d3f35,0x3e953f7f3f0e3f7b,
0x3f7a3efc3f7f3e48,0x3f273f6a3f5c3f3e,0xbf31bf65bf62bf35,0xbdfbbf7cbedbbf7d,0x3f13bf1d3e95bf55,0x3f73bcc93f4ebeac,0xbf6f3d97bf463ec4,0xbf77bf09bf80be79,
0xbe603f5f3dc93f7b,0xbf423ecfbf043f2c,0x3f39bee63ef1bf35,0x3f7e3e2f3f67be16,0x3f513f4a3f753f0e,0x3ea13f803f183f71,0xbeb8bf7fbf22bf6d,0x3e89bf58bd49bf78,
0xbf4e3edbbf0e3f35,0xbf80be79bf753dc9,0x3f04bf3e3e48bf6d,0x3f71be163f46bef1,0xbf7dbeacbf7b0000,0xbf2cbf5cbf62bf22,0x3f78bd493f55bec4,0x3f673f183f7f3e95,
0xbf18bf67bf55bf35,0x3d49bf78be95bf7f,0x3f5c3f2c3f7b3ec4,0x3eac3f7d3f223f62,0x3e16bf71be48bf80,0x3f3ebf043ef1bf46,0x3e793f803f0e3f6d,0xbedb3f4ebdc93f75,
0x3ee6bf583dc9bf7b,0x3f6fbe893f3ebf18,0xbf1d3f39be953f6d,0xbf7c3d97bf5c3edb,0x3f42bf133ef1bf55,0x3f803dfb3f71be79,0xbf5f3ecfbf223f35,0xbf7abea1bf7d3d49,
0x3f653f093f7f3e48,0x3eb83f773f2c3f4e,0xbf4abf31bf75bec4,0xbe2fbf7fbf04bf67,0x3f273f513f623f0e,0xbcc93f7e3eac3f78,0xbefcbf6abf46bf35,0x3e60bf73be16bf80,
0xbec43f6d00003f80,0xbf6d3ec4bf353f35,0x3ec4bf6d0000bf80,0x3f6dbec43f35bf35,0xbec43f6d00003f80,0xbf6d3ec4bf353f35,0x3ec4bf6d0000bf80,0x3f6dbec43f35bf35,
0xbf6dbec4bf808000,0xbec4bf6dbf35bf35,0x3f6d3ec43f808000,0x3ec43f6d3f353f35,0xbf6dbec4bf808000,0xbec4bf6dbf35bf35,0x3f6d3ec43f808000,0x3ec43f6d3f353f35,
0xbd97bf7cbef1bf55,0x3f31bf4a3eacbf78,0x3e893f6f3f223f35,0xbf093f65be163f80,0x3ea1bf7abdc9bf7b,0x3f6abefc3f2cbf4e,0xbdfb3f803e953f6d,0xbf513f27bf043f67,
0x3f7fbe2f3f62bf0e,0x3f393f1d3f713e79,0xbf773eb8bf463f35,0xbf58bee6bf7dbd49,0x3f733e603f7fbe48,0x3ecf3f5f3f3e3f18,0xbf7ebcc9bf753ec4,0xbf13bf42bf5cbedb,
0x3e163f713f0e3f35,0xbf2c3f5cbe953f7f,0x3e79bf80be48bf6d,0x3f67bf183f22bf62,0x3f4e3edb3f7b0000,0x3d493f783ef13f46,0xbf04bf3ebf55bec4,0x3eacbf7dbdc9bf75,
0xbf7d3eacbf553f35,0xbf3ebf04bf75bdc9,0x3f783d493f7bbec4,0x3edb3f4e3f463ef1,0xbf183f67be483f80,0xbf803e79bf623f22,0x3f5cbf2c3f0ebf6d,0x3f713e163f7fbe95,
0x3e2fbf7ebe95bf55,0x3f65bf313f18bf71,0x3ecf3f423f463ec4,0xbefc3f7abd493f78,0xbf58be89bf7f3e48,0xbd97bf6fbf04bf2c,0x3f80bea13f62bf35,0x3f1d3f133f673e16,
0x3f7cbdfb3f75bf0e,0x3ee63f393f4e3eac,0xbf6a3f27bf223f6d,0xbf5fbe60bf803e79,0x3f09bf773dc9bf7b,0x3f7fbeb83f5cbf3e,0x3cc93f733ef13f35,0xbf4a3f51bedb3f7d,
0x3f46bf623ec4bf80,0x3f75bdc93f7bbf0e,0xbf7f3e95bf6d3f35,0xbef1bf22bf55be48,0x3f223ef13f6d0000,0xbe953f7f3e483f55,0x3dc9bf75bec4bf35,0x3f62bf463f0ebf7b,
0x3f223ef13f6d8000,0xbe953f7f3e483f55,0x3dc9bf75bec4bf35,0x3f62bf463f0ebf7b,0xbf463f62bec43f80,0xbf753dc9bf7b3f0e,0x3f7fbe953f6dbf35,0x3ef13f223f553e48,
0xbf6f3f42bf223f7b,0xbf4abe2fbf7d3eac,0x3e60bf77be95bf35,0x3f73bf393f2cbf78,0x3cc9bf65bef1bf0e,0x3f5fbf583f04bf80,0x3f513dfb3f7fbec4,0xbd973f6a3edb3f18,
0xbeb8bf27bf46be48,0x3f1dbf7c3e16bf71,0x3f7abe893f75bf35,0x3ea13f313f3e3e79,0x3f80bee63f62bf55,0x3efc3f093f5c3d49,0xbf133f7ebdc93f6d,0xbf7f3ecfbf673f4e,
0x3f71be793f7bbf35,0x3e163f3e3f223e95,0xbd49bf4ebf0ebec4,0x3f5cbf673ef1bf7f,0xbedbbf04bf550000,0x3f18bf803dc9bf62,0xbf2c3f7dbe483f6d,0xbf783eacbf753f46,
0xbeac3f783e483f35,0xbf7d3f2cbf463f75,0x3f80bf183f55bf6d,0x3f043edb3f62bdc9,0x3f67bf5c3f0ebf80,0x3f4e3d493f7fbef1,0xbf3ebe16bf7b3ec4,0x3e79bf71be95bf22,
0xbdfbbf31bf22be48,0x3f58bf733edbbf78,0x3f7fbf133f62bf6d,0x3eb83efc3f4ebd49,0xbe893f6a3e953f0e,0xbf7c3f42bf3e3f7d,0xbf653e60bf7f3f35,0x3cc9bf4abf04beac,
0x3f7ebf393f46bf7b,0x3f093ea13f67be79,0xbd973f513ef13ec4,0xbf6f3f5fbf183f80,0xbf773ecfbf753f55,0xbe2fbf27bf2cbe16,0x3ee6bf7abdc9bf35,0x3f80bf1d3f5cbf71,
0xbf7b3f55bf353f80,0xbf0ebe48bf6d3ec4,0x3e483f0e3f350000,0xbf553f7bbec43f6d,0x3f7bbf553f35bf80,0x3f0e3e483f6dbec4,0xbe48bf0ebf350000,0x3f55bf7b3ec4bf6d,
0xbe48bf0ebf358000,0x3f55bf7b3ec4bf6d,0xbf7b3f55bf353f80,0xbf0ebe48bf6d3ec4,0x3e483f0e3f358000,0xbf553f7bbec43f6d,0x3f7bbf553f35bf80,0x3f0e3e483f6dbec4,
0x3f1d3cc93f75bf0e,0xbf093f733d493f18,0xbf273f7cbdc93f35,0xbf6f3efcbf783f67,0xbe89becfbf463e48,0x3f51bf7f3eacbf5c,0x3f65bf7a3ef1bf6d,0x3f39bdfb3f7dbf2c,
0xbf4a3f80be953f55,0xbf583ea1bf803f4e,0xbf423e2fbf7f3f35,0x3eb8bf5fbe79bedb,0x3f77bf6a3f22bf7b,0x3f133d973f71bf04,0x3ee63e603f62bec4,0xbf313f7ebe163f3e,
0x3f3ebf7d3e48bf35,0x3f5cbedb3f7fbf62,0xbeacbe79bf553ec4,0x3f4ebf803e95bf46,0xbd493f183f0e0000,0xbf783f71bf223f75,0x3f67bf043f7bbf6d,0xbe163f2c3ef13dc9,
0x3f2cbe163f7bbf35,0xbf043f673dc93ef1,0x3f71bf783f0ebf6d,0x3f18bd493f75bf22,0xbf803f4ebf553f80,0xbe79beacbf463e95,0xbedb3f5c3e483ec4,0xbf7d3f3ebf623f7f,
0xbecfbd97bf623f0e,0x3f4abf7c3e79bf2c,0x3f09bf5fbdc9bec4,0x3f73bf313f71bf7d,0x3f80bf653f46bf7b,0x3e893e603f4ebedb,0x3f13bdfb3f75bf35,0xbf273f6fbd493f04,
0x3f6abf7f3ef1bf55,0x3f1dbe2f3f78bf3e,0x3f58befc3f7fbf6d,0xbea13f393eac3e16,0x3cc93ee63f22be48,0xbf773f7abf183f67,0xbf513f7ebe953f35,0xbf423eb8bf803f5c,
0x3f75bf463f6dbf80,0xbdc93ef13f0ebe48,0x3f62bf7f3ec4bf35,0x3f22be953f7bbf55,0x3e95bf22bec40000,0x3f7fbf623f55bf7b,0xbef13dc9bf6d3f35,0x3f46bf753e48bf0e,
0xbe953f223ec48000,0xbf7f3f62bf553f7b,0x3ef1bdc93f6dbf35,0xbf463f75be483f0e,0x3f75bf463f6dbf80,0xbdc93ef13f0ebe48,0x3f62bf7f3ec4bf35,0x3f22be953f7bbf55,
0x3f13bf4abdc9be48,0x3f65bf393f78bf80,0x3f6fbf7f3ef1bf35,0x3efcbe603f71bf4e,0xbf093e89bf753f55,0x3f42bf6a3e16bedb,0x3cc9bea1bf223ec4,0x3f7ebf7c3f2cbf5c,
0x3f51bf1d3f7fbf7b,0xbee63f313e793d49,0x3eb8bd973f62bf35,0xbf5f3f7abeac3f18,0x3f58bf773e95bf0e,0x3f27becf3f7dbf67,0x3f80bf733f46bf6d,0x3dfb3e2f3f3ebf04,
0xbe793d49bf553f35,0x3f71bf7d3ef1bf22,0xbf183edbbf7b3f6d,0x3f3ebf5c3dc9be95,0x3f04bf2cbe480000,0x3f67bf4e3f75bf7f,0x3e16beacbf0e3ec4,0x3f80bf783f46bf62,
0x3f78bf803f0ebf35,0x3eacbe163f62bf46,0x3f4ebf673e48bec4,0x3f2cbf043f7fbf75,0x3f5cbf3e3f7bbf80,0xbedb3f183e95bdc9,0x3f7dbf713f55bf6d,0xbd493e793f22bef1,
0xbf273f13bf7f3f7b,0x3f39bf4a3d49be16,0xbefc3ecfbf753f6d,0x3f58bf653e79beac,0xbea13e60bf623f55,0x3f6fbf773edbbf04,0xbdfb3cc9bf463f35,0x3f7cbf7f3f18bf2c,
0x3f42bf513dc9be48,0x3f31bf1d3f80bf7d,0x3f5fbf6a3e95bec4,0x3f09bee63f78bf71,0x3f73bf7a3ef1bf0e,0x3eb8be893f67bf5c,0x3f7ebf803f22bf35,0x3e2fbd973f4ebf3e,
0x3f803f80,0xbf80bf80,0x3f803f80,0xbf80bf80,0x3f803f80,0xbf80bf80,0x3f803f80,0xbf80bf80,
0xbf80bf8080008000,0x3f803f8080008000,0xbf80bf8080008000,0x3f803f8080008000,0xbf80bf8080008000,0x3f803f8080008000,0xbf80bf8080008000,0x3f803f8080008000,
0xbea1be603f753f7b,0x3eb83e89bf71bf78,0xbdfbbcc93f7f3f80,0x3e2f3d97bf7dbf80,0xbf27bf133f463f55,0x3f313f1dbf3ebf4e,0xbefcbecf3f623f6d,0x3f093ee6bf5cbf67,
0xbf73bf7abe95be48,0x3f6f3f773eac3e79,0xbf7ebf80bdc98000,0x3f7c3f7f3e163d49,0xbf42bf51bf22bf0e,0x3f393f4a3f2c3f18,0xbf5fbf6abef1bec4,0x3f583f653f043edb,
0xbf5cbf3e3f0e3f35,0x3f673f4ebef1bf22,0xbf7dbf713e483ec4,0x3f803f78bdc9be95,0xbe79bd493f7b3f80,0x3eac3e16bf75bf7f,0xbf18bedb3f553f6d,0x3f2c3f04bf46bf62,
0xbf04bf2cbf55bf35,0x3edb3f183f623f46,0xbe16beacbf7bbf6d,0x3d493e793f7f3f75,0xbf78bf80be488000,0x3f713f7d3e953dc9,0xbf4ebf67bf0ebec4,0x3f3e3f5c3f223ef1,
0xbf58bf77bef1be48,0x3f423f6a3f183eac,0xbf80bf733dc93ec4,0x3f7e3f7c3d49be79,0xbf51bf1d3f223f55,0x3f653f39bf04bf3e,0xbeb8bd973f753f80,0x3efc3e60bf67bf7d,
0x3f093e89bf62bf7b,0xbf27becf3f4e3f71,0xbcc9bea1bf7fbf6d,0xbdfb3e2f3f803f78,0xbf13bf4abf46bf0e,0x3ee63f313f5c3f2c,0xbf6fbf7fbe958000,0x3f5f3f7a3edb3e16,
0xbef1bdc93f6d3f80,0x3f223e95bf55bf7b,0xbf75bf463ec43f35,0x3f7f3f62be48bf0e,0xbf62bf7fbec40000,0x3f463f753f0e3e48,0xbe95bf22bf6dbf35,0x3dc93ef13f7b3f55,
0xbf62bf7fbec48000,0x3f463f753f0e3e48,0xbe95bf22bf6dbf35,0x3dc93ef13f7b3f55,0x3ef13dc9bf6dbf80,0xbf22be953f553f7b,0x3f753f46bec4bf35,0xbf7fbf623e483f0e,
0xbf80bf653dc93f0e,0x3f773f7a3e16beac,0xbf13bdfb3f623f80,0x3f423eb8bf3ebf78,0x3ecfbd97bf75bf7b,0xbf1dbe2f3f5c3f80,0xbf09bf5fbf46bec4,0x3ea13f393f673f18,
0x3cc9bee6bf7fbf55,0xbe893e603f7d3f71,0xbf51bf7ebef18000,0x3f273f6f3f2c3e79,0x3f6a3f7f3e95be48,0xbf4abf7cbf04bd49,0x3f583efcbf22bf6d,0xbf73bf313edb3f4e,
0xbd49bf18bf7bbf35,0xbe793eac3f7f3f62,0x3f673f04bf0ebf6d,0xbf7dbf3e3e953f46,0xbf2cbe163f553f80,0x3f5c3edbbf22bf75,0xbf71bf78be483ec4,0x3f4e3f803ef1bdc9,
0x3f803f4ebe48bf35,0xbf78bf71bdc93ef1,0x3edb3f5c3f553ec4,0xbe16bf2cbf75bf22,0xbf3ebf7dbf0e8000,0x3f043f673f463e95,0x3eacbe79bf7bbf6d,0xbf18bd493f623f7f,
0x3f773f6a3dc9bf0e,0xbf51bf7fbedb3e79,0x3ee6be60bf75bf6d,0xbf39bdfb3f4e3f80,0xbf4abf80bef13e48,0x3f093f733f3e3e16,0xbf42be2f3f463f80,0x3f6f3efcbf04bf71,
0xbe893ecf3f7f3f55,0x3f13bd97bf67bf78,0x3f653f7a3e95bec4,0xbf31bf7ebf183d49,0x3f1dbcc9bf62bf7b,0xbf58bea13f2c3f7d,0xbf27bf7cbf228000,0x3eb83f5f3f5c3eac,
0xbf55be483f353f80,0x3f7b3f0ebec4bf6d,0xbf0ebf7bbf350000,0x3e483f553f6d3ec4,0x3f553e48bf35bf80,0xbf7bbf0e3ec43f6d,0x3f0e3f7b3f350000,0xbe48bf55bf6dbec4,
0xbf0ebf7bbf358000,0x3e483f553f6d3ec4,0x3f553e48bf35bf80,0xbf7bbf0e3ec43f6d,0x3f0e3f7b3f358000,0xbe48bf55bf6dbec4,0xbf55be483f353f80,0x3f7b3f0ebec4bf6d,
0xbe89bf6abf62be48,0xbe2f3f273f803f18,0xbf65be603f223f80,0x3f803f1dbe79bf67,0xbdfb3f313f7f3f0e,0x3f09bea1bf71bf5c,0x3f7f3f13be95bf6d,0xbf6fbf5fbe163f2c,
0x3f773ecfbef1bf7b,0xbf7cbf423d493f4e,0xbee6bf7abf468000,0x3cc93f4a3f783edb,0xbf7ebf393dc93f55,0x3f583f733eacbf04,0x3d973f513f753ec4,0x3eb8befcbf7dbf3e,
0x3f673f5c3e48bf35,0xbf18bf80bf223e95,0xbf3e3e163f553f6d,0x3f783eacbef1bf7f,0xbf71be793f0e3f80,0x3f7d3f2cbdc9bf62,0x3d49bf4ebf7bbec4,0xbf043edb3f753f46,
0xbedb3f043f7b3f35,0x3f4ebd49bf46bf75,0xbf2cbf7dbf0e3ec4,0x3e793f713f623dc9,0xbeacbf78bf558000,0xbe163f3e3f7f3ef1,0x3f803f18be48bf6d,0xbf5cbf67be953f22,
0xbf80bee63e953f7b,0x3f5f3f583e79bf3e,0x3f133f7e3f22bec4,0xbd97bf6abf71be16,0x3eb8bf27bf7fbf0e,0xbf4a3e2f3f4e3f67,0xbf7abe893ef13f80,0x3f733f393d49bf5c,
0xbcc9bf65bf75be48,0xbefc3f093f783f2c,0xbf513dfb3f463f6d,0x3f7f3ecfbeacbf7d,0x3f6f3f423dc9bf55,0xbf1dbf7cbf183edb,0xbe60bf77bf628000,0xbea13f313f803f04,
0xbf7fbe953ec43f80,0x3f623f463e48bf55,0x3f22bef1bf6dbf35,0xbf75bdc93f0e3f7b,0x3dc93f753f6d0000,0x3ef1bf22bf7bbf0e,0xbf46bf62bec43f35,0x3e953f7f3f55be48,
0xbdc9bf75bf6d8000,0xbef13f223f7b3f0e,0x3f463f623ec4bf35,0xbe95bf7fbf553e48,0xbf7fbe953ec43f80,0x3f623f463e48bf55,0x3f22bef1bf6dbf35,0xbf75bdc93f0e3f7b,
0x3f58be89bf46bf55,0xbf7fbeb83e793f80,0xbf80bea13e953f80,0x3f4a3f513eacbf4e,0xbe2fbf7ebf623e48,0xbee63f393f7d3edb,0xbecf3f423f7f3ec4,0x3f5fbe60bf3ebf5c,
0x3f093f773f22bf0e,0x3d97bf6fbf78bd49,0x3cc9bf73bf758000,0xbf1d3f133f713f18,0x3f7c3dfbbef1bf7b,0xbf65bf31be163f67,0xbf6abf27bdc93f6d,0x3efc3f7a3f2cbf04,
0xbf4e3edb3f553f35,0x3f803e79be95bf7f,0x3f04bf3ebf7bbec4,0xbf713e163f223f62,0xbf7dbeac3e483f80,0x3f2c3f5c3ef1bf46,0x3f78bd49bf0ebf6d,0xbf67bf18bdc93f75,
0xbf18bf67bf0e3f35,0xbd493f783f75bdc9,0x3f5c3f2c3e48bf6d,0xbeacbf7dbf463ef1,0x3e16bf71bf7b8000,0xbf3e3f043f623f22,0x3e793f803f55bec4,0x3edbbf4ebf7fbe95,
0x3f73be60bf22bf55,0xbf6abefcbd493f7d,0xbf7e3cc93ef13f6d,0x3f513f273e79bf71,0x3f7f3e2fbe95bf7b,0xbf31bf4abedb3f5c,0xbf77beb83dc93f80,0x3f093f653f18bf3e,
0x3ea13f7a3f46bf0e,0x3ecfbf5fbf80be16,0xbdfbbf80bf623ec4,0xbf133f423f783eac,0xbd973f7c3f75be48,0x3f39bf1dbf67bf04,0x3e89bf6fbf7f8000,0xbf583ee63f4e3f2c,
0xbf6dbec400003f80,0x3ec43f6d3f35bf35,0x3f6d3ec40000bf80,0xbec4bf6dbf353f35,0xbf6dbec400003f80,0x3ec43f6d3f35bf35,0x3f6d3ec40000bf80,0xbec4bf6dbf353f35,
0x3ec4bf6dbf808000,0xbf6d3ec43f353f35,0xbec43f6d3f808000,0x3f6dbec4bf35bf35,0x3ec4bf6dbf808000,0xbf6d3ec43f353f35,0xbec43f6d3f808000,0x3f6dbec4bf35bf35,
0x3f423f133e95bf7b,0xbcc9bf7ebf673f04,0xbf5fbecfbdc93f80,0x3e603f733f4ebf2c,0x3ee63f583f22bf55,0x3eb8bf77bf803e16,0xbf1dbf39bef13f6d,0xbe2f3f7f3f78beac,
0xbf273f513f753e48,0x3f80bdfbbedbbf5c,0x3efcbf6abf7f8000,0xbf7a3ea13f183f3e,0xbf653f093f463f0e,0x3f6f3e89bd49bf7d,0x3f4abf31bf62bec4,0xbf7cbd973e793f71,
0xbe16bf71bf553f35,0xbf2c3f5c3f753dc9,0xbe793f803f7bbec4,0x3f67bf18bf46bef1,0xbf4ebedbbe483f80,0x3d493f783f62bf22,0x3f043f3e3f0ebf6d,0x3eacbf7dbf7f3e95,
0x3f7dbeacbf0ebf35,0xbf3ebf04be953f7f,0xbf78bd493e483f6d,0x3edb3f4e3f22bf62,0x3f18bf67bf7b8000,0xbf803e793ef13f46,0xbf5c3f2c3f553ec4,0x3f713e16bdc9bf75,
0xbf513f4a3f623e48,0x3f733cc9be16bf67,0x3eb8bf7fbf7f3ec4,0xbf773f093f2c3f04,0x3e603f5f3f46bf55,0x3f27bf6abf783d49,0xbf39bee6be953f80,0xbdfb3f7c3f71bf18,
0xbf13bf1dbef13f7b,0xbea13f803f7dbedb,0x3f6f3d97bdc9bf6d,0xbe89bf58bf3e3f5c,0xbf7a3efc3f223f0e,0x3f423ecf3e79bf80,0x3f31bf65bf758000,0xbf7e3e2f3eac3f4e,
0xbf22bef1bec43f80,0xbe953f7f3f7bbf0e,0xbdc93f753f6dbf35,0x3f62bf46bf55be48,0x3f46bf62bf6d0000,0xbf753dc93e483f55,0xbf7f3e953ec43f35,0x3ef13f223f0ebf7b,
0x3f46bf62bf6d8000,0xbf753dc93e483f55,0xbf7f3e953ec43f35,0x3ef13f223f0ebf7b,0x3f223ef13ec4bf80,0x3e95bf7fbf7b3f0e,0x3dc9bf75bf6d3f35,0xbf623f463f553e48,
0xbecf3f7f3f7fbf0e,0x3f7ebf13bf18bedb,0xbf09befcbef13f80,0xbee63f803f80bf04,0xbf31bea1be953f7b,0xbe893f7a3f78bf2c,0x3f7cbf1dbf22bec4,0xbf27beb8beac3f7d,
0xbf6a3d973dc93f55,0x3dfb3f513f4ebf67,0x3f58bf5fbf628000,0xbf653cc93d493f5c,0x3f39bf73bf753e48,0xbf773e603e793f3e,0x3e2f3f4a3f46bf6d,0x3f42bf6fbf713e16,
0x3f71be79be48bf35,0xbe16bf3ebf463f75,0xbd49bf4ebf553f6d,0xbf5c3f673f62bdc9,0xbedbbf04bf0e3f80,0xbf183f803f7fbef1,0xbf2c3f7d3f7bbec4,0x3f78beacbe95bf22,
0xbeac3f783f7bbf35,0x3f7dbf2cbf22be95,0x3f80bf18bf0ebec4,0xbf04bedbbef13f7f,0x3f67bf5cbf558000,0xbf4ebd49bdc93f62,0xbf3ebe16be483f6d,0xbe793f713f75bf46,
0x3f1dbf80bf7f3f0e,0xbf7a3ee63eac3f04,0x3f273e2f3e95bf6d,0x3ecfbf77bf7d3f3e,0xbf5f3f6f3f62be48,0x3f51bd973d49bf4e,0xbea1bf09bf223f80,0xbf393f7e3f78bedb,
0x3f4abcc93dc9bf55,0x3e60bf65bf713f5c,0xbf423f7c3f75bec4,0x3f6abe89be16bf2c,0xbefcbeb8bef13f7b,0xbf133f7f3f80bf18,0x3f73bf58bf468000,0xbf31bdfbbe793f67,
0xbe48bf0ebf353f80,0xbf553f7b3f6dbec4,0xbf7b3f553f350000,0x3f0e3e483ec4bf6d,0x3e483f0e3f35bf80,0x3f55bf7bbf6d3ec4,0x3f7bbf55bf350000,0xbf0ebe48bec43f6d,
0x3f7bbf55bf358000,0xbf0ebe48bec43f6d,0xbe48bf0ebf353f80,0xbf553f7b3f6dbec4,0xbf7b3f553f358000,0x3f0e3e483ec4bf6d,0x3e483f0e3f35bf80,0x3f55bf7bbf6d3ec4,
0xbf7e3f313ef13e48,0x3e603ee63f2cbf7d,0xbd97bf13bf463f80,0xbf6a3f773f5cbeac,0x3f5fbeb8bdc9bf0e,0x3e2fbf42bf673f78,0xbea13f583f75bf6d,0x3f80bf4abf18bd49,
0x3dfbbf39bf623f7b,0xbf7a3f653f3ebe16,0x3f7fbf51bf228000,0xbecfbe89bf043f71,0xbefc3f6f3f7fbf55,0x3f7cbf27bedbbe79,0xbf733f093e953ec4,0x3cc93f1d3f4ebf80,
0xbf3e3f7d3f7bbf35,0x3f5cbedbbdc9bef1,0x3eac3e793f0ebf6d,0x3f4ebf80bf753f22,0x3d49bf18bf553f80,0xbf783f713f46be95,0xbf673f043e483ec4,0xbe163f2c3f62bf7f,
0xbf2c3e16be483f35,0xbf043f673f7fbf62,0xbf713f783f55bec4,0x3f18bd493e95bf46,0x3f80bf4ebf0e8000,0xbe79beacbf223f75,0x3edbbf5cbf7b3f6d,0xbf7d3f3e3ef13dc9,
0xbeb83f423f75bf7b,0x3f7ebf51bf043d49,0xbf7a3f773f46bec4,0x3ee63cc93edbbf4e,0xbf393ea1bdc93f0e,0xbefc3f583f7dbf71,0x3e2fbf1dbf623f80,0xbf7f3f6a3f2cbe79,
0xbf6f3f273e953e48,0xbdfb3f133f5cbf80,0xbe60be89bf223f6d,0xbf653f803f67bf18,0x3f31bf73bf7f3f55,0xbf5f3f093e163eac,0x3f7cbf4abef18000,0xbd97becfbf3e3f78,
0x3e95bf22bf6d3f80,0xbf7f3f623f0ebe48,0xbef13dc9bec43f35,0xbf463f753f7bbf55,0xbf753f463ec40000,0xbdc93ef13f55bf7b,0xbf623f7f3f6dbf35,0x3f22be953e48bf0e,
0x3f75bf46bec48000,0x3dc9bef1bf553f7b,0x3f62bf7fbf6d3f35,0xbf223e95be483f0e,0x3e95bf22bf6d3f80,0xbf7f3f623f0ebe48,0xbef13dc9bec43f35,0xbf463f753f7bbf55,
0xbe2fbdfbbf223f55,0xbf733f803f5cbf2c,0x3ecfbf27bf753f80,0xbf773f583edbbe16,0xbf7a3f5f3ef1be48,0xbd973eb83f4ebf71,0xbf313ee6bdc93ec4,0xbf1d3f513f80bf78,
0x3f7cbf7ebf463f0e,0xbea13cc9bf043f3e,0x3f6abf42be958000,0x3e89bf09bf673f7d,0x3e60befcbf623f7b,0xbf7f3f6f3f18beac,0x3f39bf65bf7f3f6d,0xbf4a3f133d493e79,
0xbe793d49bf0e3f35,0xbf713f7d3f62bf46,0xbf183edbbe483ec4,0xbf3e3f5c3f7fbf75,0x3f04bf2cbf7b3f80,0xbf673f4e3e95bdc9,0x3e16beacbf553f6d,0xbf803f783f22bef1,
0x3f78bf80bf553f35,0xbeac3e16bef13f22,0x3f4ebf67bf7b3f6d,0xbf2c3f04bdc93e95,0x3f5cbf3ebe488000,0x3edbbf18bf753f7f,0x3f7dbf71bf0e3ec4,0x3d49be79bf463f62,
0x3d97be2fbf463f55,0xbf803f7e3f2cbf18,0x3e89beb8bf623f6d,0xbf7a3f733f04bedb,0x3ee6bf09bf753f7b,0xbf6a3f5f3eacbe79,0x3f1dbf31bf7f3f80,0xbf513f423e16bd49,
0x3f7fbf7cbf223f0e,0x3cc9bdfbbf3e3f4e,0x3f77bf6fbef13ec4,0x3e60bea1bf5c3f67,0x3f65bf58be953e48,0x3ecfbefcbf713f78,0x3f4abf39bdc98000,0x3f13bf27bf7d3f80,
0x3f803f80,0xbf80bf80,0x3f803f80,0xbf80bf80,0x3f803f80,0xbf80bf80,0x3f803f80,0xbf80bf80,
0xbf80bf8080008000,0x3f803f8080008000,0xbf80bf8080008000,0x3f803f8080008000,0xbf80bf8080008000,0x3f803f8080008000,0xbf80bf8080008000,0x3f803f8080008000,
0xbf65bf583ef13f0e,0x3f6a3f5fbedbbf04,0xbf4abf393f223f35,0x3f513f42bf18bf2c,0xbf7fbf7c3dc93e48,0x3f803f7ebd49be16,0xbf77bf6f3e953ec4,0x3f7a3f73be79beac,
0xbee6bf09bf62bf55,0x3ecf3efc3f673f5c,0xbf1dbf31bf46bf35,0x3f133f273f4e3f3e,0xbd97be2fbf7fbf7b,0x3cc93dfb3f803f7d,0xbe89beb8bf75bf6d,0x3e603ea13f783f71,
0xbf04bf2cbf55bf35,0x3edb3f183f623f46,0xbe16beacbf7bbf6d,0x3d493e793f7f3f75,0xbf78bf80be480000,0x3f713f7d3e953dc9,0xbf4ebf67bf0ebec4,0x3f3e3f5c3f223ef1,
0x3f5c3f3ebf0ebf35,0xbf67bf4e3ef13f22,0x3f7d3f71be48bec4,0xbf80bf783dc93e95,0x3e793d49bf7bbf80,0xbeacbe163f753f7f,0x3f183edbbf55bf6d,0xbf2cbf043f463f62,
0x3f7a3f5fbe95bf0e,0xbf7fbf6f3e163edb,0x3f313ee6bf46bf6d,0xbf4abf133f2c3f5c,0x3e2fbdfbbf7fbf7b,0xbea1bcc93f783f80,0xbecfbf27bf62bf35,0x3e893f093f713f4e,
0x3e603efc3f753f55,0xbd97beb8bf7dbf67,0x3f393f653f223ec4,0xbf1dbf51bf3ebf04,0x3f7c3f7e3dc9be48,0xbf73bf80be793d49,0x3f6a3f42bef1bf35,0xbf77bf583eac3f18,
0x3ef13dc9bf6dbf80,0xbf22be953f553f7b,0x3f753f46bec4bf35,0xbf7fbf623e483f0e,0x3f623f7f3ec40000,0xbf46bf75bf0ebe48,0x3e953f223f6d3f35,0xbdc9bef1bf7bbf55,
0x3f623f7f3ec48000,0xbf46bf75bf0ebe48,0x3e953f223f6d3f35,0xbdc9bef1bf7bbf55,0xbef1bdc93f6d3f80,0x3f223e95bf55bf7b,0xbf75bf463ec43f35,0x3f7f3f62be48bf0e,
0x3f313f733f223e48,0xbefcbf58bf4ebedb,0x3f7c3f4abe95bf35,0xbf7fbf6a3d493f04,0xbf6fbf273ef13f55,0x3f7e3f51be79bf2c,0xbe603e893f7f3f6d,0x3ee6bcc9bf71bf7d,
0xbf39bea13f463f7b,0x3f5f3f09bf18bf67,0x3e2f3f1d3f753f35,0x3d97becfbf80bf5c,0xbeb8bf42bf62bf0e,0x3dfb3f133f783f3e,0xbf7abf77bdc93ec4,0x3f653f803eacbe16,
0xbf80bf4e3e483f35,0x3f783f713dc9bef1,0xbedbbf5cbf55bec4,0x3e163f2c3f753f22,0x3f3e3f7d3f0e0000,0xbf04bf67bf46be95,0xbeac3e793f7b3f6d,0x3f183d49bf62bf7f,
0xbd49bf18bf7bbf35,0xbe793eac3f7f3f62,0x3f673f04bf0ebf6d,0xbf7dbf3e3e953f46,0xbf2cbe163f553f80,0x3f5c3edbbf22bf75,0xbf71bf78be483ec4,0x3f4e3f803ef1bdc9,
0x3f5f3eb8bf22bf7b,0xbf7cbf273eac3f5c,0xbea1bf58bf62bec4,0xbcc93f1d3f7d3f2c,0xbf7ebf313e953f55,0x3f7a3f653d49bf18,0xbd973f133f7f3f35,0x3ecfbe89bf78bf67,
0x3efc3f6f3f463e48,0xbe2fbf42bf71bf04,0x3f733f09bef1bf6d,0xbf80bf4a3e163f3e,0xbdfbbf39bf75bf0e,0xbe603ee63f803f4e,0xbf7fbf513dc93f35,0x3f6a3f773e79bedb,
0xbf55be483f353f80,0x3f7b3f0ebec4bf6d,0xbf0ebf7bbf350000,0x3e483f553f6d3ec4,0x3f553e48bf35bf80,0xbf7bbf0e3ec43f6d,0x3f0e3f7b3f350000,0xbe48bf55bf6dbec4,
0xbf0ebf7bbf358000,0x3e483f553f6d3ec4,0x3f553e48bf35bf80,0xbf7bbf0e3ec43f6d,0x3f0e3f7b3f358000,0xbe48bf55bf6dbec4,0xbf55be483f353f80,0x3f7b3f0ebec4bf6d,
0x3efcbeb8bf75bf55,0xbf51bd973f3e3f7d,0xbf73bf58bdc93f35,0x3f393f7e3f04beac,0xbf4abcc93f463f7b,0x3f7a3ee6bedbbf78,0x3f423f7c3ef1bec4,0xbecfbf77bf4ebd49,
0x3f5f3f6f3e95bf0e,0xbf13bf7fbf2c3e16,0x3ea1bf09bf7fbf35,0xbf313dfb3f5c3f71,0xbf1dbf80bf223e48,0x3e603f653f673e79,0xbf273e2f3f623f6d,0x3f6a3e89bf18bf80,
0xbedb3f043f7b3f35,0x3f4ebd49bf46bf75,0xbf2cbf7dbf0e3ec4,0x3e793f713f623dc9,0xbeacbf78bf550000,0xbe163f3e3f7f3ef1,0x3f803f18be48bf6d,0xbf5cbf67be953f22,
0xbf67bf5cbe483f35,0x3f183f803f22be95,0x3f3ebe16bf55bf6d,0xbf78beac3ef13f7f,0x3f713e79bf0ebf80,0xbf7dbf2c3dc93f62,0xbd493f4e3f7b3ec4,0x3f04bedbbf75bf46,
0x3f31bea1bf62bf55,0xbf77be603f043f80,0xbf7cbf1d3dc93f6d,0x3f423f6f3edbbf18,0x3ecf3f7f3f46be48,0x3dfbbf51bf7dbeac,0x3f09befcbf75bf35,0xbf65bcc93f2c3f78,
0x3f393f733ef1bf0e,0xbe89bf7abf5c3d49,0x3e2fbf4abf7fbec4,0xbf273eb83f673f4e,0xbf6abd973f223f7b,0x3f7e3f13be16bf71,0x3f583f5f3e95bf35,0xbee6bf80bf3e3e79,
0x3f7f3e95bec4bf80,0xbf62bf46be483f55,0xbf223ef13f6d3f35,0x3f753dc9bf0ebf7b,0xbdc9bf75bf6d0000,0xbef13f223f7b3f0e,0x3f463f623ec4bf35,0xbe95bf7fbf553e48,
0x3dc93f753f6d8000,0x3ef1bf22bf7bbf0e,0xbf46bf62bec43f35,0x3e953f7f3f55be48,0x3f7f3e95bec4bf80,0xbf62bf46be483f55,0xbf223ef13f6d3f35,0x3f753dc9bf0ebf7b,
0xbf7abefc3dc93f7b,0x3f273f6a3f04bf2c,0x3f313f653ef1bf35,0xbdfbbf7cbf673e16,0xbf133f1d3f753f0e,0x3f73bcc9bf18bf71,0x3f6fbd97bf22bf6d,0xbf77bf093d493f78,
0x3e60bf5fbf7fbe48,0xbf423ecf3f5c3f3e,0xbf393ee63f623f35,0x3f7e3e2fbedbbf7d,0xbf51bf4abe953f55,0x3ea13f803f4ebeac,0x3eb83f7f3f46bec4,0x3e89bf58bf80be79,
0x3f183f673f0ebf35,0x3d49bf78bf753dc9,0xbf5cbf2cbe483f6d,0x3eac3f7d3f46bef1,0xbe163f713f7b0000,0x3f3ebf04bf62bf22,0xbe79bf80bf553ec4,0xbedb3f4e3f7f3e95,
0xbf4e3edb3f553f35,0x3f803e79be95bf7f,0x3f04bf3ebf7bbec4,0xbf713e163f223f62,0xbf7dbeac3e483f80,0x3f2c3f5c3ef1bf46,0x3f78bd49bf0ebf6d,0xbf67bf18bdc93f75,
0x3ee6bf58bf7fbe48,0xbf6f3e893f2c3f4e,0xbf1d3f393f753ec4,0x3f7cbd97bf04bf67,0x3f42bf13bf62bf0e,0xbf80bdfb3eac3f78,0xbf5f3ecf3f463f35,0x3f7a3ea1be16bf80,
0x3f653f093dc9bf7b,0xbeb8bf77bf3e3f18,0xbf4abf31be953f6d,0x3e2f3f7f3f5cbedb,0x3f273f513ef1bf55,0x3cc9bf7ebf713e79,0xbefcbf6abf223f35,0xbe603f733f7dbd49,
0xbf6dbec400003f80,0x3ec43f6d3f35bf35,0x3f6d3ec40000bf80,0xbec4bf6dbf353f35,0xbf6dbec400003f80,0x3ec43f6d3f35bf35,0x3f6d3ec40000bf80,0xbec4bf6dbf353f35,
0x3ec4bf6dbf808000,0xbf6d3ec43f353f35,0xbec43f6d3f808000,0x3f6dbec4bf35bf35,0x3ec4bf6dbf808000,0xbf6d3ec43f353f35,0xbec43f6d3f808000,0x3f6dbec4bf35bf35,
0x3d973f7c3f62bf0e,0x3f31bf4abf71be79,0xbe89bf6fbf463f35,0xbf093f653f7d3d49,0xbea13f7a3f7fbe48,0x3f6abefcbf3ebf18,0x3dfbbf80bf753ec4,0xbf513f273f5c3edb,
0xbf7f3e2f3ef13f55,0x3f393f1d3eacbf78,0x3f77beb8bf22bf35,0xbf58bee6be163f80,0xbf73be603dc93f7b,0x3ecf3f5f3f2cbf4e,0x3f7e3cc9be95bf6d,0xbf13bf42bf043f67,
0x3f7dbeacbf0ebf35,0xbf3ebf04be953f7f,0xbf78bd493e483f6d,0x3edb3f4e3f22bf62,0x3f18bf67bf7b0000,0xbf803e793ef13f46,0xbf5c3f2c3f553ec4,0x3f713e16bdc9bf75,
0x3e163f713f55bf35,0x3f2cbf5cbf75bdc9,0x3e79bf80bf7b3ec4,0xbf673f183f463ef1,0x3f4e3edb3e48bf80,0xbd49bf78bf623f22,0xbf04bf3ebf0e3f6d,0xbeac3f7d3f7fbe95,
0x3e2fbf7ebf753f0e,0xbf653f313f4e3eac,0x3ecf3f423f22bf6d,0x3efcbf7abf803e79,0xbf58be89bdc93f7b,0x3d973f6f3f5cbf3e,0x3f80bea1bef1bf35,0xbf1dbf13bedb3f7d,
0x3f7cbdfbbe95bf55,0xbee6bf39bf183f71,0xbf6a3f273f463ec4,0x3f5f3e603d49bf78,0x3f09bf77bf7f3e48,0xbf7f3eb83f043f2c,0x3cc93f733f62bf35,0x3f4abf51bf67be16,
0x3f223ef13ec4bf80,0x3e95bf7fbf7b3f0e,0x3dc9bf75bf6d3f35,0xbf623f463f553e48,0xbf463f623f6d0000,0x3f75bdc9be48bf55,0x3f7fbe95bec4bf35,0xbef1bf22bf0e3f7b,
0xbf463f623f6d8000,0x3f75bdc9be48bf55,0x3f7fbe95bec4bf35,0xbef1bf22bf0e3f7b,0xbf22bef1bec43f80,0xbe953f7f3f7bbf0e,0xbdc93f753f6dbf35,0x3f62bf46bf55be48,
0x3f6fbf42bf46be48,0xbf4abe2fbe163f71,0xbe603f773f75bf35,0x3f73bf39bf3ebe79,0xbcc93f653f62bf55,0x3f5fbf58bf5cbd49,0xbf51bdfbbdc93f6d,0xbd973f6a3f67bf4e,
0x3eb83f273f22bf7b,0x3f1dbf7cbf7d3eac,0xbf7a3e893e953f35,0x3ea13f313f2cbf78,0xbf803ee63ef13f0e,0x3efc3f093f04bf80,0x3f13bf7ebf7f3ec4,0xbf7f3ecf3edb3f18,
0x3eacbf78bf7b3f35,0xbf7d3f2c3f223e95,0xbf803f183f0e3ec4,0x3f043edb3ef1bf7f,0xbf673f5c3f550000,0x3f4e3d493dc9bf62,0x3f3e3e163e48bf6d,0x3e79bf71bf753f46,
0x3f71be79be48bf35,0xbe16bf3ebf463f75,0xbd49bf4ebf553f6d,0xbf5c3f673f62bdc9,0xbedbbf04bf0e3f80,0xbf183f803f7fbef1,0xbf2c3f7d3f7bbec4,0x3f78beacbe95bf22,
0xbdfbbf31bf463f7b,0xbf583f733f67be79,0x3f7fbf13bef1bec4,0xbeb8befcbf183f80,0xbe893f6a3f75bf55,0x3f7cbf42bf2cbe16,0xbf653e603dc93f35,0xbcc93f4a3f5cbf71,
0x3f7ebf39bf22be48,0xbf09bea1bedb3f78,0xbd973f513f62bf6d,0x3f6fbf5fbf4e3d49,0xbf773ecf3e953f0e,0x3e2f3f273f3ebf7d,0x3ee6bf7abf7f3f35,0xbf803f1d3f043eac,
0xbe48bf0ebf353f80,0xbf553f7b3f6dbec4,0xbf7b3f553f350000,0x3f0e3e483ec4bf6d,0x3e483f0e3f35bf80,0x3f55bf7bbf6d3ec4,0x3f7bbf55bf350000,0xbf0ebe48bec43f6d,
0x3f7bbf55bf358000,0xbf0ebe48bec43f6d,0xbe48bf0ebf353f80,0xbf553f7b3f6dbec4,0xbf7b3f553f358000,0x3f0e3e483ec4bf6d,0x3e483f0e3f35bf80,0x3f55bf7bbf6d3ec4,
0xbf1dbcc9be953f55,0xbf093f733f80bf4e,0x3f27bf7cbf7f3f35,0xbf6f3efc3e793edb,0x3e893ecf3f22bf7b,0x3f51bf7fbf713f04,0xbf653f7a3f62bec4,0x3f39bdfb3e16bf3e,
0x3f4abf80bf753f0e,0xbf583ea13d493f18,0x3f42be2f3dc9bf35,0x3eb8bf5fbf783f67,0xbf773f6a3f46be48,0x3f133d973eacbf5c,0xbee6be60bef13f6d,0xbf313f7e3f7dbf2c,
0xbf2c3e16be483f35,0xbf043f673f7fbf62,0xbf713f783f55bec4,0x3f18bd493e95bf46,0x3f80bf4ebf0e0000,0xbe79beacbf223f75,0x3edbbf5cbf7b3f6d,0xbf7d3f3e3ef13dc9,
0x3f3ebf7dbf7b3f35,0xbf5c3edb3dc93ef1,0xbeacbe79bf0e3f6d,0xbf4e3f803f75bf22,0xbd493f183f55bf80,0x3f78bf71bf463e95,0x3f67bf04be48bec4,0x3e16bf2cbf623f7f,
0xbecfbd97bef13f55,0xbf4a3f7c3f78bf3e,0x3f09bf5fbf7f3f6d,0xbf733f313eac3e16,0x3f80bf65bf223e48,0xbe89be60bf183f67,0x3f13bdfb3e95bf35,0x3f27bf6fbf803f5c,
0x3f6abf7fbf623f0e,0xbf1d3e2fbe793f2c,0x3f58befcbdc9bec4,0x3ea1bf39bf713f7d,0x3cc93ee63f46bf7b,0x3f77bf7abf4e3edb,0xbf513f7e3f75bf35,0x3f42beb83d49bf04,
0xbe953f223f6dbf80,0x3f7fbf62bf0e3e48,0x3ef1bdc93ec4bf35,0x3f46bf75bf7b3f55,0x3f75bf46bec40000,0x3dc9bef1bf553f7b,0x3f62bf7fbf6d3f35,0xbf223e95be483f0e,
0xbf753f463ec48000,0xbdc93ef13f55bf7b,0xbf623f7f3f6dbf35,0x3f22be953e48bf0e,0xbe953f223f6dbf80,0x3f7fbf62bf0e3e48,0x3ef1bdc93ec4bf35,0x3f46bf75bf7b3f55,
0xbf133f4a3f7fbf7b,0x3f65bf39be79bd49,0xbf6f3f7f3f62bf35,0x3efcbe603eacbf18,0x3f09be893e95bf0e,0x3f42bf6abf7d3f67,0xbcc93ea13f46bf6d,0x3f7ebf7cbf3e3f04,
0xbf513f1d3dc93e48,0xbee63f313f78bf80,0xbeb83d97bef13f35,0xbf5f3f7a3f71bf4e,0xbf583f773f75bf55,0x3f27becf3e16bedb,0xbf803f733f22bec4,0x3dfb3e2f3f2cbf5c,
0xbf783f803f55bf35,0x3eacbe163ef1bf22,0xbf4e3f673f7bbf6d,0x3f2cbf043dc9be95,0xbf5c3f3e3e480000,0xbedb3f183f75bf7f,0xbf7d3f713f0ebec4,0xbd493e793f46bf62,
0xbe793d49bf0e3f35,0xbf713f7d3f62bf46,0xbf183edbbe483ec4,0xbf3e3f5c3f7fbf75,0x3f04bf2cbf7b3f80,0xbf673f4e3e95bdc9,0x3e16beacbf553f6d,0xbf803f783f22bef1,
0xbf273f13bdc93e48,0xbf393f4a3f80bf7d,0xbefc3ecfbe953ec4,0xbf583f653f78bf71,0xbea13e60bef13f0e,0xbf6f3f773f67bf5c,0xbdfb3cc9bf223f35,0xbf7c3f7f3f4ebf3e,
0x3f42bf51bf7f3f7b,0xbf313f1dbd493e16,0x3f5fbf6abf753f6d,0xbf093ee6be793eac,0x3f73bf7abf623f55,0xbeb83e89bedb3f04,0x3f7ebf80bf463f35,0xbe2f3d97bf183f2c,
0x3f803f80,0xbf80bf80,0x3f803f80,0xbf80bf80,0x3f803f80,0xbf80bf80,0x3f803f80,0xbf80bf80,
0xbf80bf8080008000,0x3f803f8080008000,0xbf80bf8080008000,0x3f803f8080008000,0xbf80bf8080008000,0x3f803f8080008000,0xbf80bf8080008000,0x3f803f8080008000,
0xbf73bf7abe95be48,0x3f6f3f773eac3e79,0xbf7ebf80bdc90000,0x3f7c3f7f3e163d49,0xbf42bf51bf22bf0e,0x3f393f4a3f2c3f18,0xbf5fbf6abef1bec4,0x3f583f653f043edb,
0x3ea13e60bf75bf7b,0xbeb8be893f713f78,0x3dfb3cc9bf7fbf80,0xbe2fbd973f7d3f80,0x3f273f13bf46bf55,0xbf31bf1d3f3e3f4e,0x3efc3ecfbf62bf6d,0xbf09bee63f5c3f67,
0x3f5c3f3ebf0ebf35,0xbf67bf4e3ef13f22,0x3f7d3f71be48bec4,0xbf80bf783dc93e95,0x3e793d49bf7bbf80,0xbeacbe163f753f7f,0x3f183edbbf55bf6d,0xbf2cbf043f463f62,
0x3f043f2c3f553f35,0xbedbbf18bf62bf46,0x3e163eac3f7b3f6d,0xbd49be79bf7fbf75,0x3f783f803e488000,0xbf71bf7dbe95bdc9,0x3f4e3f673f0e3ec4,0xbf3ebf5cbf22bef1,
0xbf09be893f623f7b,0x3f273ecfbf4ebf71,0x3cc93ea13f7f3f6d,0x3dfbbe2fbf80bf78,0x3f133f4a3f463f0e,0xbee6bf31bf5cbf2c,0x3f6f3f7f3e950000,0xbf5fbf7abedbbe16,
0xbf58bf77bef1be48,0x3f423f6a3f183eac,0xbf80bf733dc93ec4,0x3f7e3f7c3d49be79,0xbf51bf1d3f223f55,0x3f653f39bf04bf3e,0xbeb8bd973f753f80,0x3efc3e60bf67bf7d,
0xbef1bdc93f6d3f80,0x3f223e95bf55bf7b,0xbf75bf463ec43f35,0x3f7f3f62be48bf0e,0xbf62bf7fbec40000,0x3f463f753f0e3e48,0xbe95bf22bf6dbf35,0x3dc93ef13f7b3f55,
0xbf62bf7fbec48000,0x3f463f753f0e3e48,0xbe95bf22bf6dbf35,0x3dc93ef13f7b3f55,0x3ef13dc9bf6dbf80,0xbf22be953f553f7b,0x3f753f46bec4bf35,0xbf7fbf623e483f0e,
0x3cc9bee6bf7fbf55,0xbe893e603f7d3f71,0xbf51bf7ebef10000,0x3f273f6f3f2c3e79,0x3f6a3f7f3e95be48,0xbf4abf7cbf04bd49,0x3f583efcbf22bf6d,0xbf73bf313edb3f4e,
0x3f803f65bdc9bf0e,0xbf77bf7abe163eac,0x3f133dfbbf62bf80,0xbf42beb83f3e3f78,0xbecf3d973f753f7b,0x3f1d3e2fbf5cbf80,0x3f093f5f3f463ec4,0xbea1bf39bf67bf18,
0x3d493f183f7b3f35,0x3e79beacbf7fbf62,0xbf67bf043f0e3f6d,0x3f7d3f3ebe95bf46,0x3f2c3e16bf55bf80,0xbf5cbedb3f223f75,0x3f713f783e48bec4,0xbf4ebf80bef13dc9,
0xbf80bf4e3e483f35,0x3f783f713dc9bef1,0xbedbbf5cbf55bec4,0x3e163f2c3f753f22,0x3f3e3f7d3f0e8000,0xbf04bf67bf46be95,0xbeac3e793f7b3f6d,0x3f183d49bf62bf7f,
0x3e89becfbf7fbf55,0xbf133d973f673f78,0xbf65bf7abe953ec4,0x3f313f7e3f18bd49,0xbf1d3cc93f623f7b,0x3f583ea1bf2cbf7d,0x3f273f7c3f220000,0xbeb8bf5fbf5cbeac,
0x3f773f6a3dc9bf0e,0xbf51bf7fbedb3e79,0x3ee6be60bf75bf6d,0xbf39bdfb3f4e3f80,0xbf4abf80bef13e48,0x3f093f733f3e3e16,0xbf42be2f3f463f80,0x3f6f3efcbf04bf71,
0xbf55be483f353f80,0x3f7b3f0ebec4bf6d,0xbf0ebf7bbf350000,0x3e483f553f6d3ec4,0x3f553e48bf35bf80,0xbf7bbf0e3ec43f6d,0x3f0e3f7b3f350000,0xbe48bf55bf6dbec4,
0xbf0ebf7bbf358000,0x3e483f553f6d3ec4,0x3f553e48bf35bf80,0xbf7bbf0e3ec43f6d,0x3f0e3f7b3f358000,0xbe48bf55bf6dbec4,0xbf55be483f353f80,0x3f7b3f0ebec4bf6d,
0x3f773ecfbef1bf7b,0xbf7cbf423d493f4e,0xbee6bf7abf460000,0x3cc93f4a3f783edb,0xbf7ebf393dc93f55,0x3f583f733eacbf04,0x3d973f513f753ec4,0x3eb8befcbf7dbf3e,
0x3e893f6a3f623e48,0x3e2fbf27bf80bf18,0x3f653e60bf22bf80,0xbf80bf1d3e793f67,0x3dfbbf31bf7fbf0e,0xbf093ea13f713f5c,0xbf7fbf133e953f6d,0x3f6f3f5f3e16bf2c,
0xbf67bf5cbe483f35,0x3f183f803f22be95,0x3f3ebe16bf55bf6d,0xbf78beac3ef13f7f,0x3f713e79bf0ebf80,0xbf7dbf2c3dc93f62,0xbd493f4e3f7b3ec4,0x3f04bedbbf75bf46,
0x3edbbf04bf7bbf35,0xbf4e3d493f463f75,0x3f2c3f7d3f0ebec4,0xbe79bf71bf62bdc9,0x3eac3f783f558000,0x3e16bf3ebf7fbef1,0xbf80bf183e483f6d,0x3f5c3f673e95bf22,
0x3cc93f653f753e48,0x3efcbf09bf78bf2c,0x3f51bdfbbf46bf6d,0xbf7fbecf3eac3f7d,0xbf6fbf42bdc93f55,0x3f1d3f7c3f18bedb,0x3e603f773f620000,0x3ea1bf31bf80bf04,
0xbf80bee63e953f7b,0x3f5f3f583e79bf3e,0x3f133f7e3f22bec4,0xbd97bf6abf71be16,0x3eb8bf27bf7fbf0e,0xbf4a3e2f3f4e3f67,0xbf7abe893ef13f80,0x3f733f393d49bf5c,
0xbf7fbe953ec43f80,0x3f623f463e48bf55,0x3f22bef1bf6dbf35,0xbf75bdc93f0e3f7b,0x3dc93f753f6d0000,0x3ef1bf22bf7bbf0e,0xbf46bf62bec43f35,0x3e953f7f3f55be48,
0xbdc9bf75bf6d8000,0xbef13f223f7b3f0e,0x3f463f623ec4bf35,0xbe95bf7fbf553e48,0xbf7fbe953ec43f80,0x3f623f463e48bf55,0x3f22bef1bf6dbf35,0xbf75bdc93f0e3f7b,
0x3f093f773f22bf0e,0x3d97bf6fbf78bd49,0x3cc9bf73bf750000,0xbf1d3f133f713f18,0x3f7c3dfbbef1bf7b,0xbf65bf31be163f67,0xbf6abf27bdc93f6d,0x3efc3f7a3f2cbf04,
0xbf583e893f463f55,0x3f7f3eb8be79bf80,0x3f803ea1be95bf80,0xbf4abf51beac3f4e,0x3e2f3f7e3f62be48,0x3ee6bf39bf7dbedb,0x3ecfbf42bf7fbec4,0xbf5f3e603f3e3f5c,
0x3f4ebedbbf55bf35,0xbf80be793e953f7f,0xbf043f3e3f7b3ec4,0x3f71be16bf22bf62,0x3f7d3eacbe48bf80,0xbf2cbf5cbef13f46,0xbf783d493f0e3f6d,0x3f673f183dc9bf75,
0x3f183f673f0ebf35,0x3d49bf78bf753dc9,0xbf5cbf2cbe483f6d,0x3eac3f7d3f46bef1,0xbe163f713f7b8000,0x3f3ebf04bf62bf22,0xbe79bf80bf553ec4,0xbedb3f4e3f7f3e95,
0xbea1bf7abf463f0e,0xbecf3f5f3f803e16,0x3dfb3f803f62bec4,0x3f13bf42bf78beac,0x3d97bf7cbf753e48,0xbf393f1d3f673f04,0xbe893f6f3f7f0000,0x3f58bee6bf4ebf2c,
0x3f73be60bf22bf55,0xbf6abefcbd493f7d,0xbf7e3cc93ef13f6d,0x3f513f273e79bf71,0x3f7f3e2fbe95bf7b,0xbf31bf4abedb3f5c,0xbf77beb83dc93f80,0x3f093f653f18bf3e,
0xbf6dbec400003f80,0x3ec43f6d3f35bf35,0x3f6d3ec40000bf80,0xbec4bf6dbf353f35,0xbf6dbec400003f80,0x3ec43f6d3f35bf35,0x3f6d3ec40000bf80,0xbec4bf6dbf353f35,
0x3ec4bf6dbf808000,0xbf6d3ec43f353f35,0xbec43f6d3f808000,0x3f6dbec4bf35bf35,0x3ec4bf6dbf808000,0xbf6d3ec43f353f35,0xbec43f6d3f808000,0x3f6dbec4bf35bf35,
0xbf273f513f753e48,0x3f80bdfbbedbbf5c,0x3efcbf6abf7f0000,0xbf7a3ea13f183f3e,0xbf653f093f463f0e,0x3f6f3e89bd49bf7d,0x3f4abf31bf62bec4,0xbf7cbd973e793f71,
0xbf42bf13be953f7b,0x3cc93f7e3f67bf04,0x3f5f3ecf3dc9bf80,0xbe60bf73bf4e3f2c,0xbee6bf58bf223f55,0xbeb83f773f80be16,0x3f1d3f393ef1bf6d,0x3e2fbf7fbf783eac,
0x3e163f713f55bf35,0x3f2cbf5cbf75bdc9,0x3e79bf80bf7b3ec4,0xbf673f183f463ef1,0x3f4e3edb3e48bf80,0xbd49bf78bf623f22,0xbf04bf3ebf0e3f6d,0xbeac3f7d3f7fbe95,
0xbf7d3eac3f0e3f35,0x3f3e3f043e95bf7f,0x3f783d49be48bf6d,0xbedbbf4ebf223f62,0xbf183f673f7b8000,0x3f80be79bef1bf46,0x3f5cbf2cbf55bec4,0xbf71be163dc93f75,
0x3f133f1d3ef1bf7b,0x3ea1bf80bf7d3edb,0xbf6fbd973dc93f6d,0x3e893f583f3ebf5c,0x3f7abefcbf22bf0e,0xbf42becfbe793f80,0xbf313f653f750000,0x3f7ebe2fbeacbf4e,
0xbf513f4a3f623e48,0x3f733cc9be16bf67,0x3eb8bf7fbf7f3ec4,0xbf773f093f2c3f04,0x3e603f5f3f46bf55,0x3f27bf6abf783d49,0xbf39bee6be953f80,0xbdfb3f7c3f71bf18,
0xbf22bef1bec43f80,0xbe953f7f3f7bbf0e,0xbdc93f753f6dbf35,0x3f62bf46bf55be48,0x3f46bf62bf6d0000,0xbf753dc93e483f55,0xbf7f3e953ec43f35,0x3ef13f223f0ebf7b,
0x3f46bf62bf6d8000,0xbf753dc93e483f55,0xbf7f3e953ec43f35,0x3ef13f223f0ebf7b,0x3f223ef13ec4bf80,0x3e95bf7fbf7b3f0e,0x3dc9bf75bf6d3f35,0xbf623f463f553e48,
0xbf6a3d973dc93f55,0x3dfb3f513f4ebf67,0x3f58bf5fbf620000,0xbf653cc93d493f5c,0x3f39bf73bf753e48,0xbf773e603e793f3e,0x3e2f3f4a3f46bf6d,0x3f42bf6fbf713e16,
0x3ecfbf7fbf7f3f0e,0xbf7e3f133f183edb,0x3f093efc3ef1bf80,0x3ee6bf80bf803f04,0x3f313ea13e95bf7b,0x3e89bf7abf783f2c,0xbf7c3f1d3f223ec4,0x3f273eb83eacbf7d,
0xbf713e793e483f35,0x3e163f3e3f46bf75,0x3d493f4e3f55bf6d,0x3f5cbf67bf623dc9,0x3edb3f043f0ebf80,0x3f18bf80bf7f3ef1,0x3f2cbf7dbf7b3ec4,0xbf783eac3e953f22,
0x3eacbf78bf7b3f35,0xbf7d3f2c3f223e95,0xbf803f183f0e3ec4,0x3f043edb3ef1bf7f,0xbf673f5c3f558000,0x3f4e3d493dc9bf62,0x3f3e3e163e48bf6d,0x3e79bf71bf753f46,
0xbf4a3cc9bdc93f55,0xbe603f653f71bf5c,0x3f42bf7cbf753ec4,0xbf6a3e893e163f2c,0x3efc3eb83ef1bf7b,0x3f13bf7fbf803f18,0xbf733f583f460000,0x3f313dfb3e79bf67,
0x3f1dbf80bf7f3f0e,0xbf7a3ee63eac3f04,0x3f273e2f3e95bf6d,0x3ecfbf77bf7d3f3e,0xbf5f3f6f3f62be48,0x3f51bd973d49bf4e,0xbea1bf09bf223f80,0xbf393f7e3f78bedb,
0xbe48bf0ebf353f80,0xbf553f7b3f6dbec4,0xbf7b3f553f350000,0x3f0e3e483ec4bf6d,0x3e483f0e3f35bf80,0x3f55bf7bbf6d3ec4,0x3f7bbf55bf350000,0xbf0ebe48bec43f6d,
0x3f7bbf55bf358000,0xbf0ebe48bec43f6d,0xbe48bf0ebf353f80,0xbf553f7b3f6dbec4,0xbf7b3f553f358000,0x3f0e3e483ec4bf6d,0x3e483f0e3f35bf80,0x3f55bf7bbf6d3ec4,
0x3dfbbf39bf623f7b,0xbf7a3f653f3ebe16,0x3f7fbf51bf220000,0xbecfbe89bf043f71,0xbefc3f6f3f7fbf55,0x3f7cbf27bedbbe79,0xbf733f093e953ec4,0x3cc93f1d3f4ebf80,
0x3f7ebf31bef1be48,0xbe60bee6bf2c3f7d,0x3d973f133f46bf80,0x3f6abf77bf5c3eac,0xbf5f3eb83dc93f0e,0xbe2f3f423f67bf78,0x3ea1bf58bf753f6d,0xbf803f4a3f183d49,
0x3f3ebf7dbf7b3f35,0xbf5c3edb3dc93ef1,0xbeacbe79bf0e3f6d,0xbf4e3f803f75bf22,0xbd493f183f55bf80,0x3f78bf71bf463e95,0x3f67bf04be48bec4,0x3e16bf2cbf623f7f,
0x3f2cbe163e48bf35,0x3f04bf67bf7f3f62,0x3f71bf78bf553ec4,0xbf183d49be953f46,0xbf803f4e3f0e8000,0x3e793eac3f22bf75,0xbedb3f5c3f7bbf6d,0x3f7dbf3ebef1bdc9,
0x3f6fbf27be95be48,0x3dfbbf13bf5c3f80,0x3e603e893f22bf6d,0x3f65bf80bf673f18,0xbf313f733f7fbf55,0x3f5fbf09be16beac,0xbf7c3f4a3ef10000,0x3d973ecf3f3ebf78,
0xbeb83f423f75bf7b,0x3f7ebf51bf043d49,0xbf7a3f773f46bec4,0x3ee63cc93edbbf4e,0xbf393ea1bdc93f0e,0xbefc3f583f7dbf71,0x3e2fbf1dbf623f80,0xbf7f3f6a3f2cbe79,
0x3e95bf22bf6d3f80,0xbf7f3f623f0ebe48,0xbef13dc9bec43f35,0xbf463f753f7bbf55,0xbf753f463ec40000,0xbdc93ef13f55bf7b,0xbf623f7f3f6dbf35,0x3f22be953e48bf0e,
0x3f75bf46bec48000,0x3dc9bef1bf553f7b,0x3f62bf7fbf6d3f35,0xbf223e95be483f0e,0x3e95bf22bf6d3f80,0xbf7f3f623f0ebe48,0xbef13dc9bec43f35,0xbf463f753f7bbf55,
0x3f7cbf7ebf463f0e,0xbea13cc9bf043f3e,0x3f6abf42be950000,0x3e89bf09bf673f7d,0x3e60befcbf623f7b,0xbf7f3f6f3f18beac,0x3f39bf65bf7f3f6d,0xbf4a3f133d493e79,
0x3e2f3dfb3f22bf55,0x3f73bf80bf5c3f2c,0xbecf3f273f75bf80,0x3f77bf58bedb3e16,0x3f7abf5fbef13e48,0x3d97beb8bf4e3f71,0x3f31bee63dc9bec4,0x3f1dbf51bf803f78,
0x3e79bd493f0ebf35,0x3f71bf7dbf623f46,0x3f18bedb3e48bec4,0x3f3ebf5cbf7f3f75,0xbf043f2c3f7bbf80,0x3f67bf4ebe953dc9,0xbe163eac3f55bf6d,0x3f80bf78bf223ef1,
0xbf783f803f55bf35,0x3eacbe163ef1bf22,0xbf4e3f673f7bbf6d,0x3f2cbf043dc9be95,0xbf5c3f3e3e488000,0xbedb3f183f75bf7f,0xbf7d3f713f0ebec4,0xbd493e793f46bf62,
0xbf7f3f7c3f22bf0e,0xbcc93dfb3f3ebf4e,0xbf773f6f3ef1bec4,0xbe603ea13f5cbf67,0xbf653f583e95be48,0xbecf3efc3f71bf78,0xbf4a3f393dc90000,0xbf133f273f7dbf80,
0x3d97be2fbf463f55,0xbf803f7e3f2cbf18,0x3e89beb8bf623f6d,0xbf7a3f733f04bedb,0x3ee6bf09bf753f7b,0xbf6a3f5f3eacbe79,0x3f1dbf31bf7f3f80,0xbf513f423e16bd49,
0x3f803f80,0xbf80bf80,0x3f803f80,0xbf80bf80,0x3f803f80,0xbf80bf80,0x3f803f80,0xbf80bf80,
0xbf80bf8080008000,0x3f803f8080008000,0xbf80bf8080008000,0x3f803f8080008000,0xbf80bf8080008000,0x3f803f8080008000,0xbf80bf8080008000,0x3f803f8080008000,
0xbee6bf09bf62bf55,0x3ecf3efc3f673f5c,0xbf1dbf31bf46bf35,0x3f133f273f4e3f3e,0xbd97be2fbf7fbf7b,0x3cc93dfb3f803f7d,0xbe89beb8bf75bf6d,0x3e603ea13f783f71,
0x3f653f58bef1bf0e,0xbf6abf5f3edb3f04,0x3f4a3f39bf22bf35,0xbf51bf423f183f2c,0x3f7f3f7cbdc9be48,0xbf80bf7e3d493e16,0x3f773f6fbe95bec4,0xbf7abf733e793eac,
0x3f043f2c3f553f35,0xbedbbf18bf62bf46,0x3e163eac3f7b3f6d,0xbd49be79bf7fbf75,0x3f783f803e480000,0xbf71bf7dbe95bdc9,0x3f4e3f673f0e3ec4,0xbf3ebf5cbf22bef1,
0xbf5cbf3e3f0e3f35,0x3f673f4ebef1bf22,0xbf7dbf713e483ec4,0x3f803f78bdc9be95,0xbe79bd493f7b3f80,0x3eac3e16bf75bf7f,0xbf18bedb3f553f6d,0x3f2c3f04bf46bf62,
0xbe60befcbf75bf55,0x3d973eb83f7d3f67,0xbf39bf65bf22bec4,0x3f1d3f513f3e3f04,0xbf7cbf7ebdc93e48,0x3f733f803e79bd49,0xbf6abf423ef13f35,0x3f773f58beacbf18,
0x3f7a3f5fbe95bf0e,0xbf7fbf6f3e163edb,0x3f313ee6bf46bf6d,0xbf4abf133f2c3f5c,0x3e2fbdfbbf7fbf7b,0xbea1bcc93f783f80,0xbecfbf27bf62bf35,0x3e893f093f713f4e,
0x3ef13dc9bf6dbf80,0xbf22be953f553f7b,0x3f753f46bec4bf35,0xbf7fbf623e483f0e,0x3f623f7f3ec40000,0xbf46bf75bf0ebe48,0x3e953f223f6d3f35,0xbdc9bef1bf7bbf55,
0x3f623f7f3ec48000,0xbf46bf75bf0ebe48,0x3e953f223f6d3f35,0xbdc9bef1bf7bbf55,0xbef1bdc93f6d3f80,0x3f223e95bf55bf7b,0xbf75bf463ec43f35,0x3f7f3f62be48bf0e,
0xbf39bea13f463f7b,0x3f5f3f09bf18bf67,0x3e2f3f1d3f753f35,0x3d97becfbf80bf5c,0xbeb8bf42bf62bf0e,0x3dfb3f133f783f3e,0xbf7abf77bdc93ec4,0x3f653f803eacbe16,
0xbf31bf73bf22be48,0x3efc3f583f4e3edb,0xbf7cbf4a3e953f35,0x3f7f3f6abd49bf04,0x3f6f3f27bef1bf55,0xbf7ebf513e793f2c,0x3e60be89bf7fbf6d,0xbee63cc93f713f7d,
0x3f803f4ebe48bf35,0xbf78bf71bdc93ef1,0x3edb3f5c3f553ec4,0xbe16bf2cbf75bf22,0xbf3ebf7dbf0e0000,0x3f043f673f463e95,0x3eacbe79bf7bbf6d,0xbf18bd493f623f7f,
0x3d493f183f7b3f35,0x3e79beacbf7fbf62,0xbf67bf043f0e3f6d,0x3f7d3f3ebe95bf46,0x3f2c3e16bf55bf80,0xbf5cbedb3f223f75,0x3f713f783e48bec4,0xbf4ebf80bef13dc9,
0xbefcbf6fbf46be48,0x3e2f3f423f713f04,0xbf73bf093ef13f6d,0x3f803f4abe16bf3e,0x3dfb3f393f753f0e,0x3e60bee6bf80bf4e,0x3f7f3f51bdc9bf35,0xbf6abf77be793edb,
0x3f5f3eb8bf22bf7b,0xbf7cbf273eac3f5c,0xbea1bf58bf62bec4,0xbcc93f1d3f7d3f2c,0xbf7ebf313e953f55,0x3f7a3f653d49bf18,0xbd973f133f7f3f35,0x3ecfbe89bf78bf67,
0xbf55be483f353f80,0x3f7b3f0ebec4bf6d,0xbf0ebf7bbf350000,0x3e483f553f6d3ec4,0x3f553e48bf35bf80,0xbf7bbf0e3ec43f6d,0x3f0e3f7b3f350000,0xbe48bf55bf6dbec4,
0xbf0ebf7bbf358000,0x3e483f553f6d3ec4,0x3f553e48bf35bf80,0xbf7bbf0e3ec43f6d,0x3f0e3f7b3f358000,0xbe48bf55bf6dbec4,0xbf55be483f353f80,0x3f7b3f0ebec4bf6d,
0x3f5f3f6f3e95bf0e,0xbf13bf7fbf2c3e16,0x3ea1bf09bf7fbf35,0xbf313dfb3f5c3f71,0xbf1dbf80bf223e48,0x3e603f653f673e79,0xbf273e2f3f623f6d,0x3f6a3e89bf18bf80,
0xbefc3eb83f753f55,0x3f513d97bf3ebf7d,0x3f733f583dc9bf35,0xbf39bf7ebf043eac,0x3f4a3cc9bf46bf7b,0xbf7abee63edb3f78,0xbf42bf7cbef13ec4,0x3ecf3f773f4e3d49,
0x3edbbf04bf7bbf35,0xbf4e3d493f463f75,0x3f2c3f7d3f0ebec4,0xbe79bf71bf62bdc9,0x3eac3f783f550000,0x3e16bf3ebf7fbef1,0xbf80bf183e483f6d,0x3f5c3f673e95bf22,
0x3f673f5c3e48bf35,0xbf18bf80bf223e95,0xbf3e3e163f553f6d,0x3f783eacbef1bf7f,0xbf71be793f0e3f80,0x3f7d3f2cbdc9bf62,0x3d49bf4ebf7bbec4,0xbf043edb3f753f46,
0xbf39bf73bef13f0e,0x3e893f7a3f5cbd49,0xbe2f3f4a3f7f3ec4,0x3f27beb8bf67bf4e,0x3f6a3d97bf22bf7b,0xbf7ebf133e163f71,0xbf58bf5fbe953f35,0x3ee63f803f3ebe79,
0x3f31bea1bf62bf55,0xbf77be603f043f80,0xbf7cbf1d3dc93f6d,0x3f423f6f3edbbf18,0x3ecf3f7f3f46be48,0x3dfbbf51bf7dbeac,0x3f09befcbf75bf35,0xbf65bcc93f2c3f78,
0x3f7f3e95bec4bf80,0xbf62bf46be483f55,0xbf223ef13f6d3f35,0x3f753dc9bf0ebf7b,0xbdc9bf75bf6d0000,0xbef13f223f7b3f0e,0x3f463f623ec4bf35,0xbe95bf7fbf553e48,
0x3dc93f753f6d8000,0x3ef1bf22bf7bbf0e,0xbf46bf62bec43f35,0x3e953f7f3f55be48,0x3f7f3e95bec4bf80,0xbf62bf46be483f55,0xbf223ef13f6d3f35,0x3f753dc9bf0ebf7b,
0x3e60bf5fbf7fbe48,0xbf423ecf3f5c3f3e,0xbf393ee63f623f35,0x3f7e3e2fbedbbf7d,0xbf51bf4abe953f55,0x3ea13f803f4ebeac,0x3eb83f7f3f46bec4,0x3e89bf58bf80be79,
0x3f7a3efcbdc9bf7b,0xbf27bf6abf043f2c,0xbf31bf65bef13f35,0x3dfb3f7c3f67be16,0x3f13bf1dbf75bf0e,0xbf733cc93f183f71,0xbf6f3d973f223f6d,0x3f773f09bd49bf78,
0xbf18bf67bf0e3f35,0xbd493f783f75bdc9,0x3f5c3f2c3e48bf6d,0xbeacbf7dbf463ef1,0x3e16bf71bf7b0000,0xbf3e3f043f623f22,0x3e793f803f55bec4,0x3edbbf4ebf7fbe95,
0x3f4ebedbbf55bf35,0xbf80be793e953f7f,0xbf043f3e3f7b3ec4,0x3f71be16bf22bf62,0x3f7d3eacbe48bf80,0xbf2cbf5cbef13f46,0xbf783d493f0e3f6d,0x3f673f183dc9bf75,
0xbf65bf09bdc93f7b,0x3eb83f773f3ebf18,0x3f4a3f313e95bf6d,0xbe2fbf7fbf5c3edb,0xbf27bf51bef13f55,0xbcc93f7e3f71be79,0x3efc3f6a3f22bf35,0x3e60bf73bf7d3d49,
0x3ee6bf58bf7fbe48,0xbf6f3e893f2c3f4e,0xbf1d3f393f753ec4,0x3f7cbd97bf04bf67,0x3f42bf13bf62bf0e,0xbf80bdfb3eac3f78,0xbf5f3ecf3f463f35,0x3f7a3ea1be16bf80,
0xbf6dbec400003f80,0x3ec43f6d3f35bf35,0x3f6d3ec40000bf80,0xbec4bf6dbf353f35,0xbf6dbec400003f80,0x3ec43f6d3f35bf35,0x3f6d3ec40000bf80,0xbec4bf6dbf353f35,
0x3ec4bf6dbf808000,0xbf6d3ec43f353f35,0xbec43f6d3f808000,0x3f6dbec4bf35bf35,0x3ec4bf6dbf808000,0xbf6d3ec43f353f35,0xbec43f6d3f808000,0x3f6dbec4bf35bf35,
0xbf7f3e2f3ef13f55,0x3f393f1d3eacbf78,0x3f77beb8bf22bf35,0xbf58bee6be163f80,0xbf73be603dc93f7b,0x3ecf3f5f3f2cbf4e,0x3f7e3cc9be95bf6d,0xbf13bf42bf043f67,
0xbd97bf7cbf623f0e,0xbf313f4a3f713e79,0x3e893f6f3f46bf35,0x3f09bf65bf7dbd49,0x3ea1bf7abf7f3e48,0xbf6a3efc3f3e3f18,0xbdfb3f803f75bec4,0x3f51bf27bf5cbedb,
0xbf7d3eac3f0e3f35,0x3f3e3f043e95bf7f,0x3f783d49be48bf6d,0xbedbbf4ebf223f62,0xbf183f673f7b0000,0x3f80be79bef1bf46,0x3f5cbf2cbf55bec4,0xbf71be163dc93f75,
0xbe16bf71bf553f35,0xbf2c3f5c3f753dc9,0xbe793f803f7bbec4,0x3f67bf18bf46bef1,0xbf4ebedbbe483f80,0x3d493f783f62bf22,0x3f043f3e3f0ebf6d,0x3eacbf7dbf7f3e95,
0xbf7c3dfb3e953f55,0x3ee63f393f18bf71,0x3f6abf27bf46bec4,0xbf5fbe60bd493f78,0xbf093f773f7fbe48,0x3f7fbeb8bf04bf2c,0xbcc9bf73bf623f35,0xbf4a3f513f673e16,
0x3e2fbf7ebf753f0e,0xbf653f313f4e3eac,0x3ecf3f423f22bf6d,0x3efcbf7abf803e79,0xbf58be89bdc93f7b,0x3d973f6f3f5cbf3e,0x3f80bea1bef1bf35,0xbf1dbf13bedb3f7d,
0x3f223ef13ec4bf80,0x3e95bf7fbf7b3f0e,0x3dc9bf75bf6d3f35,0xbf623f463f553e48,0xbf463f623f6d0000,0x3f75bdc9be48bf55,0x3f7fbe95bec4bf35,0xbef1bf22bf0e3f7b,
0xbf463f623f6d8000,0x3f75bdc9be48bf55,0x3f7fbe95bec4bf35,0xbef1bf22bf0e3f7b,0xbf22bef1bec43f80,0xbe953f7f3f7bbf0e,0xbdc93f753f6dbf35,0x3f62bf46bf55be48,
0x3eb83f273f22bf7b,0x3f1dbf7cbf7d3eac,0xbf7a3e893e953f35,0x3ea13f313f2cbf78,0xbf803ee63ef13f0e,0x3efc3f093f04bf80,0x3f13bf7ebf7f3ec4,0xbf7f3ecf3edb3f18,
0xbf6f3f423f463e48,0x3f4a3e2f3e16bf71,0x3e60bf77bf753f35,0xbf733f393f3e3e79,0x3cc9bf65bf623f55,0xbf5f3f583f5c3d49,0x3f513dfb3dc9bf6d,0x3d97bf6abf673f4e,
0xbeac3f783f7bbf35,0x3f7dbf2cbf22be95,0x3f80bf18bf0ebec4,0xbf04bedbbef13f7f,0x3f67bf5cbf550000,0xbf4ebd49bdc93f62,0xbf3ebe16be483f6d,0xbe793f713f75bf46,
0xbf713e793e483f35,0x3e163f3e3f46bf75,0x3d493f4e3f55bf6d,0x3f5cbf67bf623dc9,0x3edb3f043f0ebf80,0x3f18bf80bf7f3ef1,0x3f2cbf7dbf7b3ec4,0xbf783eac3e953f22,
0xbf7e3f393f223e48,0x3f093ea13edbbf78,0x3d97bf51bf623f6d,0xbf6f3f5f3f4ebd49,0x3f77becfbe95bf0e,0xbe2fbf27bf3e3f7d,0xbee63f7a3f7fbf35,0x3f80bf1dbf04beac,
0xbdfbbf31bf463f7b,0xbf583f733f67be79,0x3f7fbf13bef1bec4,0xbeb8befcbf183f80,0xbe893f6a3f75bf55,0x3f7cbf42bf2cbe16,0xbf653e603dc93f35,0xbcc93f4a3f5cbf71,
0xbe48bf0ebf353f80,0xbf553f7b3f6dbec4,0xbf7b3f553f350000,0x3f0e3e483ec4bf6d,0x3e483f0e3f35bf80,0x3f55bf7bbf6d3ec4,0x3f7bbf55bf350000,0xbf0ebe48bec43f6d,
0x3f7bbf55bf358000,0xbf0ebe48bec43f6d,0xbe48bf0ebf353f80,0xbf553f7b3f6dbec4,0xbf7b3f553f358000,0x3f0e3e483ec4bf6d,0x3e483f0e3f35bf80,0x3f55bf7bbf6d3ec4,
0x3f4abf80bf753f0e,0xbf583ea13d493f18,0x3f42be2f3dc9bf35,0x3eb8bf5fbf783f67,0xbf773f6a3f46be48,0x3f133d973eacbf5c,0xbee6be60bef13f6d,0xbf313f7e3f7dbf2c,
0x3f1d3cc93e95bf55,0x3f09bf73bf803f4e,0xbf273f7c3f7fbf35,0x3f6fbefcbe79bedb,0xbe89becfbf223f7b,0xbf513f7f3f71bf04,0x3f65bf7abf623ec4,0xbf393dfbbe163f3e,
0x3f2cbe163e48bf35,0x3f04bf67bf7f3f62,0x3f71bf78bf553ec4,0xbf183d49be953f46,0xbf803f4e3f0e0000,0x3e793eac3f22bf75,0xbedb3f5c3f7bbf6d,0x3f7dbf3ebef1bdc9,
0xbf3e3f7d3f7bbf35,0x3f5cbedbbdc9bef1,0x3eac3e793f0ebf6d,0x3f4ebf80bf753f22,0x3d49bf18bf553f80,0xbf783f713f46be95,0xbf673f043e483ec4,0xbe163f2c3f62bf7f,
0xbf6a3f7f3f62bf0e,0x3f1dbe2f3e79bf2c,0xbf583efc3dc93ec4,0xbea13f393f71bf7d,0xbcc9bee6bf463f7b,0xbf773f7a3f4ebedb,0x3f51bf7ebf753f35,0xbf423eb8bd493f04,
0xbecfbd97bef13f55,0xbf4a3f7c3f78bf3e,0x3f09bf5fbf7f3f6d,0xbf733f313eac3e16,0x3f80bf65bf223e48,0xbe89be60bf183f67,0x3f13bdfb3e95bf35,0x3f27bf6fbf803f5c,
0xbe953f223f6dbf80,0x3f7fbf62bf0e3e48,0x3ef1bdc93ec4bf35,0x3f46bf75bf7b3f55,0x3f75bf46bec40000,0x3dc9bef1bf553f7b,0x3f62bf7fbf6d3f35,0xbf223e95be483f0e,
0xbf753f463ec48000,0xbdc93ef13f55bf7b,0xbf623f7f3f6dbf35,0x3f22be953e48bf0e,0xbe953f223f6dbf80,0x3f7fbf62bf0e3e48,0x3ef1bdc93ec4bf35,0x3f46bf75bf7b3f55,
0xbf513f1d3dc93e48,0xbee63f313f78bf80,0xbeb83d97bef13f35,0xbf5f3f7a3f71bf4e,0xbf583f773f75bf55,0x3f27becf3e16bedb,0xbf803f733f22bec4,0x3dfb3e2f3f2cbf5c,
0x3f13bf4abf7f3f7b,0xbf653f393e793d49,0x3f6fbf7fbf623f35,0xbefc3e60beac3f18,0xbf093e89be953f0e,0xbf423f6a3f7dbf67,0x3cc9bea1bf463f6d,0xbf7e3f7c3f3ebf04,
0x3f78bf80bf553f35,0xbeac3e16bef13f22,0x3f4ebf67bf7b3f6d,0xbf2c3f04bdc93e95,0x3f5cbf3ebe480000,0x3edbbf18bf753f7f,0x3f7dbf71bf0e3ec4,0x3d49be79bf463f62,
0x3e79bd493f0ebf35,0x3f71bf7dbf623f46,0x3f18bedb3e48bec4,0x3f3ebf5cbf7f3f75,0xbf043f2c3f7bbf80,0x3f67bf4ebe953dc9,0xbe163eac3f55bf6d,0x3f80bf78bf223ef1,
0xbf423f513f7fbf7b,0x3f31bf1d3d49be16,0xbf5f3f6a3f75bf6d,0x3f09bee63e79beac,0xbf733f7a3f62bf55,0x3eb8be893edbbf04,0xbf7e3f803f46bf35,0x3e2fbd973f18bf2c,
0xbf273f13bdc93e48,0xbf393f4a3f80bf7d,0xbefc3ecfbe953ec4,0xbf583f653f78bf71,0xbea13e60bef13f0e,0xbf6f3f773f67bf5c,0xbdfb3cc9bf223f35,0xbf7c3f7f3f4ebf3e,
0x3f803f80,0xbf80bf80,0x3f803f80,0xbf80bf80,0x3f803f80,0xbf80bf80,0x3f803f80,0xbf80bf80,
0xbf80bf8080008000,0x3f803f8080008000,0xbf80bf8080008000,0x3f803f8080008000,0xbf80bf8080008000,0x3f803f8080008000,0xbf80bf8080008000,0x3f803f8080008000,
0x3ea13e60bf75bf7b,0xbeb8be893f713f78,0x3dfb3cc9bf7fbf80,0xbe2fbd973f7d3f80,0x3f273f13bf46bf55,0xbf31bf1d3f3e3f4e,0x3efc3ecfbf62bf6d,0xbf09bee63f5c3f67,
0x3f733f7a3e953e48,0xbf6fbf77beacbe79,0x3f7e3f803dc98000,0xbf7cbf7fbe16bd49,0x3f423f513f223f0e,0xbf39bf4abf2cbf18,0x3f5f3f6a3ef13ec4,0xbf58bf65bf04bedb,
0xbf5cbf3e3f0e3f35,0x3f673f4ebef1bf22,0xbf7dbf713e483ec4,0x3f803f78bdc9be95,0xbe79bd493f7b3f80,0x3eac3e16bf75bf7f,0xbf18bedb3f553f6d,0x3f2c3f04bf46bf62,
0xbf04bf2cbf55bf35,0x3edb3f183f623f46,0xbe16beacbf7bbf6d,0x3d493e793f7f3f75,0xbf78bf80be488000,0x3f713f7d3e953dc9,0xbf4ebf67bf0ebec4,0x3f3e3f5c3f223ef1,
0x3f583f773ef13e48,0xbf42bf6abf18beac,0x3f803f73bdc9bec4,0xbf7ebf7cbd493e79,0x3f513f1dbf22bf55,0xbf65bf393f043f3e,0x3eb83d97bf75bf80,0xbefcbe603f673f7d,
0xbf09be893f623f7b,0x3f273ecfbf4ebf71,0x3cc93ea13f7f3f6d,0x3dfbbe2fbf80bf78,0x3f133f4a3f463f0e,0xbee6bf31bf5cbf2c,0x3f6f3f7f3e958000,0xbf5fbf7abedbbe16,
0xbef1bdc93f6d3f80,0x3f223e95bf55bf7b,0xbf75bf463ec43f35,0x3f7f3f62be48bf0e,0xbf62bf7fbec40000,0x3f463f753f0e3e48,0xbe95bf22bf6dbf35,0x3dc93ef13f7b3f55,
0xbf62bf7fbec48000,0x3f463f753f0e3e48,0xbe95bf22bf6dbf35,0x3dc93ef13f7b3f55,0x3ef13dc9bf6dbf80,0xbf22be953f553f7b,0x3f753f46bec4bf35,0xbf7fbf623e483f0e,
0x3f803f65bdc9bf0e,0xbf77bf7abe163eac,0x3f133dfbbf62bf80,0xbf42beb83f3e3f78,0xbecf3d973f753f7b,0x3f1d3e2fbf5cbf80,0x3f093f5f3f463ec4,0xbea1bf39bf67bf18,
0xbcc93ee63f7f3f55,0x3e89be60bf7dbf71,0x3f513f7e3ef18000,0xbf27bf6fbf2cbe79,0xbf6abf7fbe953e48,0x3f4a3f7c3f043d49,0xbf58befc3f223f6d,0x3f733f31bedbbf4e,
0xbd49bf18bf7bbf35,0xbe793eac3f7f3f62,0x3f673f04bf0ebf6d,0xbf7dbf3e3e953f46,0xbf2cbe163f553f80,0x3f5c3edbbf22bf75,0xbf71bf78be483ec4,0x3f4e3f803ef1bdc9,
0x3f803f4ebe48bf35,0xbf78bf71bdc93ef1,0x3edb3f5c3f553ec4,0xbe16bf2cbf75bf22,0xbf3ebf7dbf0e8000,0x3f043f673f463e95,0x3eacbe79bf7bbf6d,0xbf18bd493f623f7f,
0xbf77bf6abdc93f0e,0x3f513f7f3edbbe79,0xbee63e603f753f6d,0x3f393dfbbf4ebf80,0x3f4a3f803ef1be48,0xbf09bf73bf3ebe16,0x3f423e2fbf46bf80,0xbf6fbefc3f043f71,
0x3e89becfbf7fbf55,0xbf133d973f673f78,0xbf65bf7abe953ec4,0x3f313f7e3f18bd49,0xbf1d3cc93f623f7b,0x3f583ea1bf2cbf7d,0x3f273f7c3f228000,0xbeb8bf5fbf5cbeac,
0xbf55be483f353f80,0x3f7b3f0ebec4bf6d,0xbf0ebf7bbf350000,0x3e483f553f6d3ec4,0x3f553e48bf35bf80,0xbf7bbf0e3ec43f6d,0x3f0e3f7b3f350000,0xbe48bf55bf6dbec4,
0xbf0ebf7bbf358000,0x3e483f553f6d3ec4,0x3f553e48bf35bf80,0xbf7bbf0e3ec43f6d,0x3f0e3f7b3f358000,0xbe48bf55bf6dbec4,0xbf55be483f353f80,0x3f7b3f0ebec4bf6d,
0x3e893f6a3f623e48,0x3e2fbf27bf80bf18,0x3f653e60bf22bf80,0xbf80bf1d3e793f67,0x3dfbbf31bf7fbf0e,0xbf093ea13f713f5c,0xbf7fbf133e953f6d,0x3f6f3f5f3e16bf2c,
0xbf77becf3ef13f7b,0x3f7c3f42bd49bf4e,0x3ee63f7a3f468000,0xbcc9bf4abf78bedb,0x3f7e3f39bdc9bf55,0xbf58bf73beac3f04,0xbd97bf51bf75bec4,0xbeb83efc3f7d3f3e,
0x3f673f5c3e48bf35,0xbf18bf80bf223e95,0xbf3e3e163f553f6d,0x3f783eacbef1bf7f,0xbf71be793f0e3f80,0x3f7d3f2cbdc9bf62,0x3d49bf4ebf7bbec4,0xbf043edb3f753f46,
0xbedb3f043f7b3f35,0x3f4ebd49bf46bf75,0xbf2cbf7dbf0e3ec4,0x3e793f713f623dc9,0xbeacbf78bf558000,0xbe163f3e3f7f3ef1,0x3f803f18be48bf6d,0xbf5cbf67be953f22,
0x3f803ee6be95bf7b,0xbf5fbf58be793f3e,0xbf13bf7ebf223ec4,0x3d973f6a3f713e16,0xbeb83f273f7f3f0e,0x3f4abe2fbf4ebf67,0x3f7a3e89bef1bf80,0xbf73bf39bd493f5c,
0x3cc93f653f753e48,0x3efcbf09bf78bf2c,0x3f51bdfbbf46bf6d,0xbf7fbecf3eac3f7d,0xbf6fbf42bdc93f55,0x3f1d3f7c3f18bedb,0x3e603f773f628000,0x3ea1bf31bf80bf04,
0xbf7fbe953ec43f80,0x3f623f463e48bf55,0x3f22bef1bf6dbf35,0xbf75bdc93f0e3f7b,0x3dc93f753f6d0000,0x3ef1bf22bf7bbf0e,0xbf46bf62bec43f35,0x3e953f7f3f55be48,
0xbdc9bf75bf6d8000,0xbef13f223f7b3f0e,0x3f463f623ec4bf35,0xbe95bf7fbf553e48,0xbf7fbe953ec43f80,0x3f623f463e48bf55,0x3f22bef1bf6dbf35,0xbf75bdc93f0e3f7b,
0xbf583e893f463f55,0x3f7f3eb8be79bf80,0x3f803ea1be95bf80,0xbf4abf51beac3f4e,0x3e2f3f7e3f62be48,0x3ee6bf39bf7dbedb,0x3ecfbf42bf7fbec4,0xbf5f3e603f3e3f5c,
0xbf09bf77bf223f0e,0xbd973f6f3f783d49,0xbcc93f733f758000,0x3f1dbf13bf71bf18,0xbf7cbdfb3ef13f7b,0x3f653f313e16bf67,0x3f6a3f273dc9bf6d,0xbefcbf7abf2c3f04,
0xbf4e3edb3f553f35,0x3f803e79be95bf7f,0x3f04bf3ebf7bbec4,0xbf713e163f223f62,0xbf7dbeac3e483f80,0x3f2c3f5c3ef1bf46,0x3f78bd49bf0ebf6d,0xbf67bf18bdc93f75,
0xbf18bf67bf0e3f35,0xbd493f783f75bdc9,0x3f5c3f2c3e48bf6d,0xbeacbf7dbf463ef1,0x3e16bf71bf7b8000,0xbf3e3f043f623f22,0x3e793f803f55bec4,0x3edbbf4ebf7fbe95,
0xbf733e603f223f55,0x3f6a3efc3d49bf7d,0x3f7ebcc9bef1bf6d,0xbf51bf27be793f71,0xbf7fbe2f3e953f7b,0x3f313f4a3edbbf5c,0x3f773eb8bdc9bf80,0xbf09bf65bf183f3e,
0xbea1bf7abf463f0e,0xbecf3f5f3f803e16,0x3dfb3f803f62bec4,0x3f13bf42bf78beac,0x3d97bf7cbf753e48,0xbf393f1d3f673f04,0xbe893f6f3f7f8000,0x3f58bee6bf4ebf2c,
0xbf6dbec400003f80,0x3ec43f6d3f35bf35,0x3f6d3ec40000bf80,0xbec4bf6dbf353f35,0xbf6dbec400003f80,0x3ec43f6d3f35bf35,0x3f6d3ec40000bf80,0xbec4bf6dbf353f35,
0x3ec4bf6dbf808000,0xbf6d3ec43f353f35,0xbec43f6d3f808000,0x3f6dbec4bf35bf35,0x3ec4bf6dbf808000,0xbf6d3ec43f353f35,0xbec43f6d3f808000,0x3f6dbec4bf35bf35,
0xbf42bf13be953f7b,0x3cc93f7e3f67bf04,0x3f5f3ecf3dc9bf80,0xbe60bf73bf4e3f2c,0xbee6bf58bf223f55,0xbeb83f773f80be16,0x3f1d3f393ef1bf6d,0x3e2fbf7fbf783eac,
0x3f27bf51bf75be48,0xbf803dfb3edb3f5c,0xbefc3f6a3f7f8000,0x3f7abea1bf18bf3e,0x3f65bf09bf46bf0e,0xbf6fbe893d493f7d,0xbf4a3f313f623ec4,0x3f7c3d97be79bf71,
0xbe16bf71bf553f35,0xbf2c3f5c3f753dc9,0xbe793f803f7bbec4,0x3f67bf18bf46bef1,0xbf4ebedbbe483f80,0x3d493f783f62bf22,0x3f043f3e3f0ebf6d,0x3eacbf7dbf7f3e95,
0x3f7dbeacbf0ebf35,0xbf3ebf04be953f7f,0xbf78bd493e483f6d,0x3edb3f4e3f22bf62,0x3f18bf67bf7b8000,0xbf803e793ef13f46,0xbf5c3f2c3f553ec4,0x3f713e16bdc9bf75,
0x3f51bf4abf62be48,0xbf73bcc93e163f67,0xbeb83f7f3f7fbec4,0x3f77bf09bf2cbf04,0xbe60bf5fbf463f55,0xbf273f6a3f78bd49,0x3f393ee63e95bf80,0x3dfbbf7cbf713f18,
0x3f133f1d3ef1bf7b,0x3ea1bf80bf7d3edb,0xbf6fbd973dc93f6d,0x3e893f583f3ebf5c,0x3f7abefcbf22bf0e,0xbf42becfbe793f80,0xbf313f653f758000,0x3f7ebe2fbeacbf4e,
0xbf22bef1bec43f80,0xbe953f7f3f7bbf0e,0xbdc93f753f6dbf35,0x3f62bf46bf55be48,0x3f46bf62bf6d0000,0xbf753dc93e483f55,0xbf7f3e953ec43f35,0x3ef13f223f0ebf7b,
0x3f46bf62bf6d8000,0xbf753dc93e483f55,0xbf7f3e953ec43f35,0x3ef13f223f0ebf7b,0x3f223ef13ec4bf80,0x3e95bf7fbf7b3f0e,0x3dc9bf75bf6d3f35,0xbf623f463f553e48,
0x3ecfbf7fbf7f3f0e,0xbf7e3f133f183edb,0x3f093efc3ef1bf80,0x3ee6bf80bf803f04,0x3f313ea13e95bf7b,0x3e89bf7abf783f2c,0xbf7c3f1d3f223ec4,0x3f273eb83eacbf7d,
0x3f6abd97bdc9bf55,0xbdfbbf51bf4e3f67,0xbf583f5f3f628000,0x3f65bcc9bd49bf5c,0xbf393f733f75be48,0x3f77be60be79bf3e,0xbe2fbf4abf463f6d,0xbf423f6f3f71be16,
0x3f71be79be48bf35,0xbe16bf3ebf463f75,0xbd49bf4ebf553f6d,0xbf5c3f673f62bdc9,0xbedbbf04bf0e3f80,0xbf183f803f7fbef1,0xbf2c3f7d3f7bbec4,0x3f78beacbe95bf22,
0xbeac3f783f7bbf35,0x3f7dbf2cbf22be95,0x3f80bf18bf0ebec4,0xbf04bedbbef13f7f,0x3f67bf5cbf558000,0xbf4ebd49bdc93f62,0xbf3ebe16be483f6d,0xbe793f713f75bf46,
0xbf1d3f803f7fbf0e,0x3f7abee6beacbf04,0xbf27be2fbe953f6d,0xbecf3f773f7dbf3e,0x3f5fbf6fbf623e48,0xbf513d97bd493f4e,0x3ea13f093f22bf80,0x3f39bf7ebf783edb,
0xbf4a3cc9bdc93f55,0xbe603f653f71bf5c,0x3f42bf7cbf753ec4,0xbf6a3e893e163f2c,0x3efc3eb83ef1bf7b,0x3f13bf7fbf803f18,0xbf733f583f468000,0x3f313dfb3e79bf67,
0xbe48bf0ebf353f80,0xbf553f7b3f6dbec4,0xbf7b3f553f350000,0x3f0e3e483ec4bf6d,0x3e483f0e3f35bf80,0x3f55bf7bbf6d3ec4,0x3f7bbf55bf350000,0xbf0ebe48bec43f6d,
0x3f7bbf55bf358000,0xbf0ebe48bec43f6d,0xbe48bf0ebf353f80,0xbf553f7b3f6dbec4,0xbf7b3f553f358000,0x3f0e3e483ec4bf6d,0x3e483f0e3f35bf80,0x3f55bf7bbf6d3ec4,
0x3f7ebf31bef1be48,0xbe60bee6bf2c3f7d,0x3d973f133f46bf80,0x3f6abf77bf5c3eac,0xbf5f3eb83dc93f0e,0xbe2f3f423f67bf78,0x3ea1bf58bf753f6d,0xbf803f4a3f183d49,
0xbdfb3f393f62bf7b,0x3f7abf65bf3e3e16,0xbf7f3f513f228000,0x3ecf3e893f04bf71,0x3efcbf6fbf7f3f55,0xbf7c3f273edb3e79,0x3f73bf09be95bec4,0xbcc9bf1dbf4e3f80,
0xbf3e3f7d3f7bbf35,0x3f5cbedbbdc9bef1,0x3eac3e793f0ebf6d,0x3f4ebf80bf753f22,0x3d49bf18bf553f80,0xbf783f713f46be95,0xbf673f043e483ec4,0xbe163f2c3f62bf7f,
0xbf2c3e16be483f35,0xbf043f673f7fbf62,0xbf713f783f55bec4,0x3f18bd493e95bf46,0x3f80bf4ebf0e8000,0xbe79beacbf223f75,0x3edbbf5cbf7b3f6d,0xbf7d3f3e3ef13dc9,
0x3eb8bf42bf753f7b,0xbf7e3f513f04bd49,0x3f7abf77bf463ec4,0xbee6bcc9bedb3f4e,0x3f39bea13dc9bf0e,0x3efcbf58bf7d3f71,0xbe2f3f1d3f62bf80,0x3f7fbf6abf2c3e79,
0x3f6fbf27be95be48,0x3dfbbf13bf5c3f80,0x3e603e893f22bf6d,0x3f65bf80bf673f18,0xbf313f733f7fbf55,0x3f5fbf09be16beac,0xbf7c3f4a3ef18000,0x3d973ecf3f3ebf78,
0x3e95bf22bf6d3f80,0xbf7f3f623f0ebe48,0xbef13dc9bec43f35,0xbf463f753f7bbf55,0xbf753f463ec40000,0xbdc93ef13f55bf7b,0xbf623f7f3f6dbf35,0x3f22be953e48bf0e,
0x3f75bf46bec48000,0x3dc9bef1bf553f7b,0x3f62bf7fbf6d3f35,0xbf223e95be483f0e,0x3e95bf22bf6d3f80,0xbf7f3f623f0ebe48,0xbef13dc9bec43f35,0xbf463f753f7bbf55,
0x3e2f3dfb3f22bf55,0x3f73bf80bf5c3f2c,0xbecf3f273f75bf80,0x3f77bf58bedb3e16,0x3f7abf5fbef13e48,0x3d97beb8bf4e3f71,0x3f31bee63dc9bec4,0x3f1dbf51bf803f78,
0xbf7c3f7e3f46bf0e,0x3ea1bcc93f04bf3e,0xbf6a3f423e958000,0xbe893f093f67bf7d,0xbe603efc3f62bf7b,0x3f7fbf6fbf183eac,0xbf393f653f7fbf6d,0x3f4abf13bd49be79,
0xbe793d49bf0e3f35,0xbf713f7d3f62bf46,0xbf183edbbe483ec4,0xbf3e3f5c3f7fbf75,0x3f04bf2cbf7b3f80,0xbf673f4e3e95bdc9,0x3e16beacbf553f6d,0xbf803f783f22bef1,
0x3f78bf80bf553f35,0xbeac3e16bef13f22,0x3f4ebf67bf7b3f6d,0xbf2c3f04bdc93e95,0x3f5cbf3ebe488000,0x3edbbf18bf753f7f,0x3f7dbf71bf0e3ec4,0x3d49be79bf463f62,
0xbd973e2f3f46bf55,0x3f80bf7ebf2c3f18,0xbe893eb83f62bf6d,0x3f7abf73bf043edb,0xbee63f093f75bf7b,0x3f6abf5fbeac3e79,0xbf1d3f313f7fbf80,0x3f51bf42be163d49,
0xbf7f3f7c3f22bf0e,0xbcc93dfb3f3ebf4e,0xbf773f6f3ef1bec4,0xbe603ea13f5cbf67,0xbf653f583e95be48,0xbecf3efc3f71bf78,0xbf4a3f393dc98000,0xbf133f273f7dbf80,
0x3f803f80,0xbf80bf80,0x3f803f80,0xbf80bf80,0x3f803f80,0xbf80bf80,0x3f803f80,0xbf80bf80,
0xbf80bf8080008000,0x3f803f8080008000,0xbf80bf8080008000,0x3f803f8080008000,0xbf80bf8080008000,0x3f803f8080008000,0xbf80bf8080008000,0x3f803f8080008000,
0x3f653f58bef1bf0e,0xbf6abf5f3edb3f04,0x3f4a3f39bf22bf35,0xbf51bf423f183f2c,0x3f7f3f7cbdc9be48,0xbf80bf7e3d493e16,0x3f773f6fbe95bec4,0xbf7abf733e793eac,
0x3ee63f093f623f55,0xbecfbefcbf67bf5c,0x3f1d3f313f463f35,0xbf13bf27bf4ebf3e,0x3d973e2f3f7f3f7b,0xbcc9bdfbbf80bf7d,0x3e893eb83f753f6d,0xbe60bea1bf78bf71,
0xbf04bf2cbf55bf35,0x3edb3f183f623f46,0xbe16beacbf7bbf6d,0x3d493e793f7f3f75,0xbf78bf80be480000,0x3f713f7d3e953dc9,0xbf4ebf67bf0ebec4,0x3f3e3f5c3f223ef1,
0x3f5c3f3ebf0ebf35,0xbf67bf4e3ef13f22,0x3f7d3f71be48bec4,0xbf80bf783dc93e95,0x3e793d49bf7bbf80,0xbeacbe163f753f7f,0x3f183edbbf55bf6d,0xbf2cbf043f463f62,
0xbf7abf5f3e953f0e,0x3f7f3f6fbe16bedb,0xbf31bee63f463f6d,0x3f4a3f13bf2cbf5c,0xbe2f3dfb3f7f3f7b,0x3ea13cc9bf78bf80,0x3ecf3f273f623f35,0xbe89bf09bf71bf4e,
0xbe60befcbf75bf55,0x3d973eb83f7d3f67,0xbf39bf65bf22bec4,0x3f1d3f513f3e3f04,0xbf7cbf7ebdc93e48,0x3f733f803e79bd49,0xbf6abf423ef13f35,0x3f773f58beacbf18,
0x3ef13dc9bf6dbf80,0xbf22be953f553f7b,0x3f753f46bec4bf35,0xbf7fbf623e483f0e,0x3f623f7f3ec40000,0xbf46bf75bf0ebe48,0x3e953f223f6d3f35,0xbdc9bef1bf7bbf55,
0x3f623f7f3ec48000,0xbf46bf75bf0ebe48,0x3e953f223f6d3f35,0xbdc9bef1bf7bbf55,0xbef1bdc93f6d3f80,0x3f223e95bf55bf7b,0xbf75bf463ec43f35,0x3f7f3f62be48bf0e,
0xbf31bf73bf22be48,0x3efc3f583f4e3edb,0xbf7cbf4a3e953f35,0x3f7f3f6abd49bf04,0x3f6f3f27bef1bf55,0xbf7ebf513e793f2c,0x3e60be89bf7fbf6d,0xbee63cc93f713f7d,
0x3f393ea1bf46bf7b,0xbf5fbf093f183f67,0xbe2fbf1dbf75bf35,0xbd973ecf3f803f5c,0x3eb83f423f623f0e,0xbdfbbf13bf78bf3e,0x3f7a3f773dc9bec4,0xbf65bf80beac3e16,
0xbf80bf4e3e483f35,0x3f783f713dc9bef1,0xbedbbf5cbf55bec4,0x3e163f2c3f753f22,0x3f3e3f7d3f0e0000,0xbf04bf67bf46be95,0xbeac3e793f7b3f6d,0x3f183d49bf62bf7f,
0xbd49bf18bf7bbf35,0xbe793eac3f7f3f62,0x3f673f04bf0ebf6d,0xbf7dbf3e3e953f46,0xbf2cbe163f553f80,0x3f5c3edbbf22bf75,0xbf71bf78be483ec4,0x3f4e3f803ef1bdc9,
0xbf5fbeb83f223f7b,0x3f7c3f27beacbf5c,0x3ea13f583f623ec4,0x3cc9bf1dbf7dbf2c,0x3f7e3f31be95bf55,0xbf7abf65bd493f18,0x3d97bf13bf7fbf35,0xbecf3e893f783f67,
0xbefcbf6fbf46be48,0x3e2f3f423f713f04,0xbf73bf093ef13f6d,0x3f803f4abe16bf3e,0x3dfb3f393f753f0e,0x3e60bee6bf80bf4e,0x3f7f3f51bdc9bf35,0xbf6abf77be793edb,
0xbf55be483f353f80,0x3f7b3f0ebec4bf6d,0xbf0ebf7bbf350000,0x3e483f553f6d3ec4,0x3f553e48bf35bf80,0xbf7bbf0e3ec43f6d,0x3f0e3f7b3f350000,0xbe48bf55bf6dbec4,
0xbf0ebf7bbf358000,0x3e483f553f6d3ec4,0x3f553e48bf35bf80,0xbf7bbf0e3ec43f6d,0x3f0e3f7b3f358000,0xbe48bf55bf6dbec4,0xbf55be483f353f80,0x3f7b3f0ebec4bf6d,
0xbefc3eb83f753f55,0x3f513d97bf3ebf7d,0x3f733f583dc9bf35,0xbf39bf7ebf043eac,0x3f4a3cc9bf46bf7b,0xbf7abee63edb3f78,0xbf42bf7cbef13ec4,0x3ecf3f773f4e3d49,
0xbf5fbf6fbe953f0e,0x3f133f7f3f2cbe16,0xbea13f093f7f3f35,0x3f31bdfbbf5cbf71,0x3f1d3f803f22be48,0xbe60bf65bf67be79,0x3f27be2fbf62bf6d,0xbf6abe893f183f80,
0xbedb3f043f7b3f35,0x3f4ebd49bf46bf75,0xbf2cbf7dbf0e3ec4,0x3e793f713f623dc9,0xbeacbf78bf550000,0xbe163f3e3f7f3ef1,0x3f803f18be48bf6d,0xbf5cbf67be953f22,
0xbf67bf5cbe483f35,0x3f183f803f22be95,0x3f3ebe16bf55bf6d,0xbf78beac3ef13f7f,0x3f713e79bf0ebf80,0xbf7dbf2c3dc93f62,0xbd493f4e3f7b3ec4,0x3f04bedbbf75bf46,
0xbf313ea13f623f55,0x3f773e60bf04bf80,0x3f7c3f1dbdc9bf6d,0xbf42bf6fbedb3f18,0xbecfbf7fbf463e48,0xbdfb3f513f7d3eac,0xbf093efc3f753f35,0x3f653cc9bf2cbf78,
0xbf39bf73bef13f0e,0x3e893f7a3f5cbd49,0xbe2f3f4a3f7f3ec4,0x3f27beb8bf67bf4e,0x3f6a3d97bf22bf7b,0xbf7ebf133e163f71,0xbf58bf5fbe953f35,0x3ee63f803f3ebe79,
0x3f7f3e95bec4bf80,0xbf62bf46be483f55,0xbf223ef13f6d3f35,0x3f753dc9bf0ebf7b,0xbdc9bf75bf6d0000,0xbef13f223f7b3f0e,0x3f463f623ec4bf35,0xbe95bf7fbf553e48,
0x3dc93f753f6d8000,0x3ef1bf22bf7bbf0e,0xbf46bf62bec43f35,0x3e953f7f3f55be48,0x3f7f3e95bec4bf80,0xbf62bf46be483f55,0xbf223ef13f6d3f35,0x3f753dc9bf0ebf7b,
0x3f7a3efcbdc9bf7b,0xbf27bf6abf043f2c,0xbf31bf65bef13f35,0x3dfb3f7c3f67be16,0x3f13bf1dbf75bf0e,0xbf733cc93f183f71,0xbf6f3d973f223f6d,0x3f773f09bd49bf78,
0xbe603f5f3f7f3e48,0x3f42becfbf5cbf3e,0x3f39bee6bf62bf35,0xbf7ebe2f3edb3f7d,0x3f513f4a3e95bf55,0xbea1bf80bf4e3eac,0xbeb8bf7fbf463ec4,0xbe893f583f803e79,
0x3f183f673f0ebf35,0x3d49bf78bf753dc9,0xbf5cbf2cbe483f6d,0x3eac3f7d3f46bef1,0xbe163f713f7b0000,0x3f3ebf04bf62bf22,0xbe79bf80bf553ec4,0xbedb3f4e3f7f3e95,
0xbf4e3edb3f553f35,0x3f803e79be95bf7f,0x3f04bf3ebf7bbec4,0xbf713e163f223f62,0xbf7dbeac3e483f80,0x3f2c3f5c3ef1bf46,0x3f78bd49bf0ebf6d,0xbf67bf18bdc93f75,
0xbee63f583f7f3e48,0x3f6fbe89bf2cbf4e,0x3f1dbf39bf75bec4,0xbf7c3d973f043f67,0xbf423f133f623f0e,0x3f803dfbbeacbf78,0x3f5fbecfbf46bf35,0xbf7abea13e163f80,
0xbf65bf09bdc93f7b,0x3eb83f773f3ebf18,0x3f4a3f313e95bf6d,0xbe2fbf7fbf5c3edb,0xbf27bf51bef13f55,0xbcc93f7e3f71be79,0x3efc3f6a3f22bf35,0x3e60bf73bf7d3d49,
0xbf6dbec400003f80,0x3ec43f6d3f35bf35,0x3f6d3ec40000bf80,0xbec4bf6dbf353f35,0xbf6dbec400003f80,0x3ec43f6d3f35bf35,0x3f6d3ec40000bf80,0xbec4bf6dbf353f35,
0x3ec4bf6dbf808000,0xbf6d3ec43f353f35,0xbec43f6d3f808000,0x3f6dbec4bf35bf35,0x3ec4bf6dbf808000,0xbf6d3ec43f353f35,0xbec43f6d3f808000,0x3f6dbec4bf35bf35,
0xbd97bf7cbf623f0e,0xbf313f4a3f713e79,0x3e893f6f3f46bf35,0x3f09bf65bf7dbd49,0x3ea1bf7abf7f3e48,0xbf6a3efc3f3e3f18,0xbdfb3f803f75bec4,0x3f51bf27bf5cbedb,
0x3f7fbe2fbef1bf55,0xbf39bf1dbeac3f78,0xbf773eb83f223f35,0x3f583ee63e16bf80,0x3f733e60bdc9bf7b,0xbecfbf5fbf2c3f4e,0xbf7ebcc93e953f6d,0x3f133f423f04bf67,
0x3f7dbeacbf0ebf35,0xbf3ebf04be953f7f,0xbf78bd493e483f6d,0x3edb3f4e3f22bf62,0x3f18bf67bf7b0000,0xbf803e793ef13f46,0xbf5c3f2c3f553ec4,0x3f713e16bdc9bf75,
0x3e163f713f55bf35,0x3f2cbf5cbf75bdc9,0x3e79bf80bf7b3ec4,0xbf673f183f463ef1,0x3f4e3edb3e48bf80,0xbd49bf78bf623f22,0xbf04bf3ebf0e3f6d,0xbeac3f7d3f7fbe95,
0xbe2f3f7e3f75bf0e,0x3f65bf31bf4ebeac,0xbecfbf42bf223f6d,0xbefc3f7a3f80be79,0x3f583e893dc9bf7b,0xbd97bf6fbf5c3f3e,0xbf803ea13ef13f35,0x3f1d3f133edbbf7d,
0xbf7c3dfb3e953f55,0x3ee63f393f18bf71,0x3f6abf27bf46bec4,0xbf5fbe60bd493f78,0xbf093f773f7fbe48,0x3f7fbeb8bf04bf2c,0xbcc9bf73bf623f35,0xbf4a3f513f673e16,
0x3f223ef13ec4bf80,0x3e95bf7fbf7b3f0e,0x3dc9bf75bf6d3f35,0xbf623f463f553e48,0xbf463f623f6d0000,0x3f75bdc9be48bf55,0x3f7fbe95bec4bf35,0xbef1bf22bf0e3f7b,
0xbf463f623f6d8000,0x3f75bdc9be48bf55,0x3f7fbe95bec4bf35,0xbef1bf22bf0e3f7b,0xbf22bef1bec43f80,0xbe953f7f3f7bbf0e,0xbdc93f753f6dbf35,0x3f62bf46bf55be48,
0xbf6f3f423f463e48,0x3f4a3e2f3e16bf71,0x3e60bf77bf753f35,0xbf733f393f3e3e79,0x3cc9bf65bf623f55,0xbf5f3f583f5c3d49,0x3f513dfb3dc9bf6d,0x3d97bf6abf673f4e,
0xbeb8bf27bf223f7b,0xbf1d3f7c3f7dbeac,0x3f7abe89be95bf35,0xbea1bf31bf2c3f78,0x3f80bee6bef1bf0e,0xbefcbf09bf043f80,0xbf133f7e3f7fbec4,0x3f7fbecfbedbbf18,
0x3eacbf78bf7b3f35,0xbf7d3f2c3f223e95,0xbf803f183f0e3ec4,0x3f043edb3ef1bf7f,0xbf673f5c3f550000,0x3f4e3d493dc9bf62,0x3f3e3e163e48bf6d,0x3e79bf71bf753f46,
0x3f71be79be48bf35,0xbe16bf3ebf463f75,0xbd49bf4ebf553f6d,0xbf5c3f673f62bdc9,0xbedbbf04bf0e3f80,0xbf183f803f7fbef1,0xbf2c3f7d3f7bbec4,0x3f78beacbe95bf22,
0x3dfb3f313f46bf7b,0x3f58bf73bf673e79,0xbf7f3f133ef13ec4,0x3eb83efc3f18bf80,0x3e89bf6abf753f55,0xbf7c3f423f2c3e16,0x3f65be60bdc9bf35,0x3cc9bf4abf5c3f71,
0xbf7e3f393f223e48,0x3f093ea13edbbf78,0x3d97bf51bf623f6d,0xbf6f3f5f3f4ebd49,0x3f77becfbe95bf0e,0xbe2fbf27bf3e3f7d,0xbee63f7a3f7fbf35,0x3f80bf1dbf04beac,
0xbe48bf0ebf353f80,0xbf553f7b3f6dbec4,0xbf7b3f553f350000,0x3f0e3e483ec4bf6d,0x3e483f0e3f35bf80,0x3f55bf7bbf6d3ec4,0x3f7bbf55bf350000,0xbf0ebe48bec43f6d,
0x3f7bbf55bf358000,0xbf0ebe48bec43f6d,0xbe48bf0ebf353f80,0xbf553f7b3f6dbec4,0xbf7b3f553f358000,0x3f0e3e483ec4bf6d,0x3e483f0e3f35bf80,0x3f55bf7bbf6d3ec4,
0x3f1d3cc93e95bf55,0x3f09bf73bf803f4e,0xbf273f7c3f7fbf35,0x3f6fbefcbe79bedb,0xbe89becfbf223f7b,0xbf513f7f3f71bf04,0x3f65bf7abf623ec4,0xbf393dfbbe163f3e,
0xbf4a3f803f75bf0e,0x3f58bea1bd49bf18,0xbf423e2fbdc93f35,0xbeb83f5f3f78bf67,0x3f77bf6abf463e48,0xbf13bd97beac3f5c,0x3ee63e603ef1bf6d,0x3f31bf7ebf7d3f2c,
0xbf2c3e16be483f35,0xbf043f673f7fbf62,0xbf713f783f55bec4,0x3f18bd493e95bf46,0x3f80bf4ebf0e0000,0xbe79beacbf223f75,0x3edbbf5cbf7b3f6d,0xbf7d3f3e3ef13dc9,
0x3f3ebf7dbf7b3f35,0xbf5c3edb3dc93ef1,0xbeacbe79bf0e3f6d,0xbf4e3f803f75bf22,0xbd493f183f55bf80,0x3f78bf71bf463e95,0x3f67bf04be48bec4,0x3e16bf2cbf623f7f,
0x3ecf3d973ef1bf55,0x3f4abf7cbf783f3e,0xbf093f5f3f7fbf6d,0x3f73bf31beacbe16,0xbf803f653f22be48,0x3e893e603f18bf67,0xbf133dfbbe953f35,0xbf273f6f3f80bf5c,
0xbf6a3f7f3f62bf0e,0x3f1dbe2f3e79bf2c,0xbf583efc3dc93ec4,0xbea13f393f71bf7d,0xbcc9bee6bf463f7b,0xbf773f7a3f4ebedb,0x3f51bf7ebf753f35,0xbf423eb8bd493f04,
0xbe953f223f6dbf80,0x3f7fbf62bf0e3e48,0x3ef1bdc93ec4bf35,0x3f46bf75bf7b3f55,0x3f75bf46bec40000,0x3dc9bef1bf553f7b,0x3f62bf7fbf6d3f35,0xbf223e95be483f0e,
0xbf753f463ec48000,0xbdc93ef13f55bf7b,0xbf623f7f3f6dbf35,0x3f22be953e48bf0e,0xbe953f223f6dbf80,0x3f7fbf62bf0e3e48,0x3ef1bdc93ec4bf35,0x3f46bf75bf7b3f55,
0x3f13bf4abf7f3f7b,0xbf653f393e793d49,0x3f6fbf7fbf623f35,0xbefc3e60beac3f18,0xbf093e89be953f0e,0xbf423f6a3f7dbf67,0x3cc9bea1bf463f6d,0xbf7e3f7c3f3ebf04,
0x3f51bf1dbdc9be48,0x3ee6bf31bf783f80,0x3eb8bd973ef1bf35,0x3f5fbf7abf713f4e,0x3f58bf77bf753f55,0xbf273ecfbe163edb,0x3f80bf73bf223ec4,0xbdfbbe2fbf2c3f5c,
0xbf783f803f55bf35,0x3eacbe163ef1bf22,0xbf4e3f673f7bbf6d,0x3f2cbf043dc9be95,0xbf5c3f3e3e480000,0xbedb3f183f75bf7f,0xbf7d3f713f0ebec4,0xbd493e793f46bf62,
0xbe793d49bf0e3f35,0xbf713f7d3f62bf46,0xbf183edbbe483ec4,0xbf3e3f5c3f7fbf75,0x3f04bf2cbf7b3f80,0xbf673f4e3e95bdc9,0x3e16beacbf553f6d,0xbf803f783f22bef1,
0x3f27bf133dc9be48,0x3f39bf4abf803f7d,0x3efcbecf3e95bec4,0x3f58bf65bf783f71,0x3ea1be603ef1bf0e,0x3f6fbf77bf673f5c,0x3dfbbcc93f22bf35,0x3f7cbf7fbf4e3f3e,
0xbf423f513f7fbf7b,0x3f31bf1d3d49be16,0xbf5f3f6a3f75bf6d,0x3f09bee63e79beac,0xbf733f7a3f62bf55,0x3eb8be893edbbf04,0xbf7e3f803f46bf35,0x3e2fbd973f18bf2c,
0x3f803f80,0xbf80bf80,0x3f803f80,0xbf80bf80,0x3f803f80,0xbf80bf80,0x3f803f80,0xbf80bf80,
0xbf80bf8080008000,0x3f803f8080008000,0xbf80bf8080008000,0x3f803f8080008000,0xbf80bf8080008000,0x3f803f8080008000,0xbf80bf8080008000,0x3f803f8080008000,
0x3f733f7a3e953e48,0xbf6fbf77beacbe79,0x3f7e3f803dc90000,0xbf7cbf7fbe16bd49,0x3f423f513f223f0e,0xbf39bf4abf2cbf18,0x3f5f3f6a3ef13ec4,0xbf58bf65bf04bedb,
0xbea1be603f753f7b,0x3eb83e89bf71bf78,0xbdfbbcc93f7f3f80,0x3e2f3d97bf7dbf80,0xbf27bf133f463f55,0x3f313f1dbf3ebf4e,0xbefcbecf3f623f6d,0x3f093ee6bf5cbf67,
0x3f5c3f3ebf0ebf35,0xbf67bf4e3ef13f22,0x3f7d3f71be48bec4,0xbf80bf783dc93e95,0x3e793d49bf7bbf80,0xbeacbe163f753f7f,0x3f183edbbf55bf6d,0xbf2cbf043f463f62,
0x3f043f2c3f553f35,0xbedbbf18bf62bf46,0x3e163eac3f7b3f6d,0xbd49be79bf7fbf75,0x3f783f803e488000,0xbf71bf7dbe95bdc9,0x3f4e3f673f0e3ec4,0xbf3ebf5cbf22bef1,
0x3f093e89bf62bf7b,0xbf27becf3f4e3f71,0xbcc9bea1bf7fbf6d,0xbdfb3e2f3f803f78,0xbf13bf4abf46bf0e,0x3ee63f313f5c3f2c,0xbf6fbf7fbe950000,0x3f5f3f7a3edb3e16,
0x3f583f773ef13e48,0xbf42bf6abf18beac,0x3f803f73bdc9bec4,0xbf7ebf7cbd493e79,0x3f513f1dbf22bf55,0xbf65bf393f043f3e,0x3eb83d97bf75bf80,0xbefcbe603f673f7d,
0xbef1bdc93f6d3f80,0x3f223e95bf55bf7b,0xbf75bf463ec43f35,0x3f7f3f62be48bf0e,0xbf62bf7fbec40000,0x3f463f753f0e3e48,0xbe95bf22bf6dbf35,0x3dc93ef13f7b3f55,
0xbf62bf7fbec48000,0x3f463f753f0e3e48,0xbe95bf22bf6dbf35,0x3dc93ef13f7b3f55,0x3ef13dc9bf6dbf80,0xbf22be953f553f7b,0x3f753f46bec4bf35,0xbf7fbf623e483f0e,
0xbcc93ee63f7f3f55,0x3e89be60bf7dbf71,0x3f513f7e3ef10000,0xbf27bf6fbf2cbe79,0xbf6abf7fbe953e48,0x3f4a3f7c3f043d49,0xbf58befc3f223f6d,0x3f733f31bedbbf4e,
0xbf80bf653dc93f0e,0x3f773f7a3e16beac,0xbf13bdfb3f623f80,0x3f423eb8bf3ebf78,0x3ecfbd97bf75bf7b,0xbf1dbe2f3f5c3f80,0xbf09bf5fbf46bec4,0x3ea13f393f673f18,
0x3d493f183f7b3f35,0x3e79beacbf7fbf62,0xbf67bf043f0e3f6d,0x3f7d3f3ebe95bf46,0x3f2c3e16bf55bf80,0xbf5cbedb3f223f75,0x3f713f783e48bec4,0xbf4ebf80bef13dc9,
0xbf80bf4e3e483f35,0x3f783f713dc9bef1,0xbedbbf5cbf55bec4,0x3e163f2c3f753f22,0x3f3e3f7d3f0e8000,0xbf04bf67bf46be95,0xbeac3e793f7b3f6d,0x3f183d49bf62bf7f,
0xbe893ecf3f7f3f55,0x3f13bd97bf67bf78,0x3f653f7a3e95bec4,0xbf31bf7ebf183d49,0x3f1dbcc9bf62bf7b,0xbf58bea13f2c3f7d,0xbf27bf7cbf220000,0x3eb83f5f3f5c3eac,
0xbf77bf6abdc93f0e,0x3f513f7f3edbbe79,0xbee63e603f753f6d,0x3f393dfbbf4ebf80,0x3f4a3f803ef1be48,0xbf09bf73bf3ebe16,0x3f423e2fbf46bf80,0xbf6fbefc3f043f71,
0xbf55be483f353f80,0x3f7b3f0ebec4bf6d,0xbf0ebf7bbf350000,0x3e483f553f6d3ec4,0x3f553e48bf35bf80,0xbf7bbf0e3ec43f6d,0x3f0e3f7b3f350000,0xbe48bf55bf6dbec4,
0xbf0ebf7bbf358000,0x3e483f553f6d3ec4,0x3f553e48bf35bf80,0xbf7bbf0e3ec43f6d,0x3f0e3f7b3f358000,0xbe48bf55bf6dbec4,0xbf55be483f353f80,0x3f7b3f0ebec4bf6d,
0xbf77becf3ef13f7b,0x3f7c3f42bd49bf4e,0x3ee63f7a3f460000,0xbcc9bf4abf78bedb,0x3f7e3f39bdc9bf55,0xbf58bf73beac3f04,0xbd97bf51bf75bec4,0xbeb83efc3f7d3f3e,
0xbe89bf6abf62be48,0xbe2f3f273f803f18,0xbf65be603f223f80,0x3f803f1dbe79bf67,0xbdfb3f313f7f3f0e,0x3f09bea1bf71bf5c,0x3f7f3f13be95bf6d,0xbf6fbf5fbe163f2c,
0xbf67bf5cbe483f35,0x3f183f803f22be95,0x3f3ebe16bf55bf6d,0xbf78beac3ef13f7f,0x3f713e79bf0ebf80,0xbf7dbf2c3dc93f62,0xbd493f4e3f7b3ec4,0x3f04bedbbf75bf46,
0x3edbbf04bf7bbf35,0xbf4e3d493f463f75,0x3f2c3f7d3f0ebec4,0xbe79bf71bf62bdc9,0x3eac3f783f558000,0x3e16bf3ebf7fbef1,0xbf80bf183e483f6d,0x3f5c3f673e95bf22,
0xbcc9bf65bf75be48,0xbefc3f093f783f2c,0xbf513dfb3f463f6d,0x3f7f3ecfbeacbf7d,0x3f6f3f423dc9bf55,0xbf1dbf7cbf183edb,0xbe60bf77bf620000,0xbea13f313f803f04,
0x3f803ee6be95bf7b,0xbf5fbf58be793f3e,0xbf13bf7ebf223ec4,0x3d973f6a3f713e16,0xbeb83f273f7f3f0e,0x3f4abe2fbf4ebf67,0x3f7a3e89bef1bf80,0xbf73bf39bd493f5c,
0xbf7fbe953ec43f80,0x3f623f463e48bf55,0x3f22bef1bf6dbf35,0xbf75bdc93f0e3f7b,0x3dc93f753f6d0000,0x3ef1bf22bf7bbf0e,0xbf46bf62bec43f35,0x3e953f7f3f55be48,
0xbdc9bf75bf6d8000,0xbef13f223f7b3f0e,0x3f463f623ec4bf35,0xbe95bf7fbf553e48,0xbf7fbe953ec43f80,0x3f623f463e48bf55,0x3f22bef1bf6dbf35,0xbf75bdc93f0e3f7b,
0xbf09bf77bf223f0e,0xbd973f6f3f783d49,0xbcc93f733f750000,0x3f1dbf13bf71bf18,0xbf7cbdfb3ef13f7b,0x3f653f313e16bf67,0x3f6a3f273dc9bf6d,0xbefcbf7abf2c3f04,
0x3f58be89bf46bf55,0xbf7fbeb83e793f80,0xbf80bea13e953f80,0x3f4a3f513eacbf4e,0xbe2fbf7ebf623e48,0xbee63f393f7d3edb,0xbecf3f423f7f3ec4,0x3f5fbe60bf3ebf5c,
0x3f4ebedbbf55bf35,0xbf80be793e953f7f,0xbf043f3e3f7b3ec4,0x3f71be16bf22bf62,0x3f7d3eacbe48bf80,0xbf2cbf5cbef13f46,0xbf783d493f0e3f6d,0x3f673f183dc9bf75,
0x3f183f673f0ebf35,0x3d49bf78bf753dc9,0xbf5cbf2cbe483f6d,0x3eac3f7d3f46bef1,0xbe163f713f7b8000,0x3f3ebf04bf62bf22,0xbe79bf80bf553ec4,0xbedb3f4e3f7f3e95,
0x3ea13f7a3f46bf0e,0x3ecfbf5fbf80be16,0xbdfbbf80bf623ec4,0xbf133f423f783eac,0xbd973f7c3f75be48,0x3f39bf1dbf67bf04,0x3e89bf6fbf7f0000,0xbf583ee63f4e3f2c,
0xbf733e603f223f55,0x3f6a3efc3d49bf7d,0x3f7ebcc9bef1bf6d,0xbf51bf27be793f71,0xbf7fbe2f3e953f7b,0x3f313f4a3edbbf5c,0x3f773eb8bdc9bf80,0xbf09bf65bf183f3e,
0xbf6dbec400003f80,0x3ec43f6d3f35bf35,0x3f6d3ec40000bf80,0xbec4bf6dbf353f35,0xbf6dbec400003f80,0x3ec43f6d3f35bf35,0x3f6d3ec40000bf80,0xbec4bf6dbf353f35,
0x3ec4bf6dbf808000,0xbf6d3ec43f353f35,0xbec43f6d3f808000,0x3f6dbec4bf35bf35,0x3ec4bf6dbf808000,0xbf6d3ec43f353f35,0xbec43f6d3f808000,0x3f6dbec4bf35bf35,
0x3f27bf51bf75be48,0xbf803dfb3edb3f5c,0xbefc3f6a3f7f0000,0x3f7abea1bf18bf3e,0x3f65bf09bf46bf0e,0xbf6fbe893d493f7d,0xbf4a3f313f623ec4,0x3f7c3d97be79bf71,
0x3f423f133e95bf7b,0xbcc9bf7ebf673f04,0xbf5fbecfbdc93f80,0x3e603f733f4ebf2c,0x3ee63f583f22bf55,0x3eb8bf77bf803e16,0xbf1dbf39bef13f6d,0xbe2f3f7f3f78beac,
0x3e163f713f55bf35,0x3f2cbf5cbf75bdc9,0x3e79bf80bf7b3ec4,0xbf673f183f463ef1,0x3f4e3edb3e48bf80,0xbd49bf78bf623f22,0xbf04bf3ebf0e3f6d,0xbeac3f7d3f7fbe95,
0xbf7d3eac3f0e3f35,0x3f3e3f043e95bf7f,0x3f783d49be48bf6d,0xbedbbf4ebf223f62,0xbf183f673f7b8000,0x3f80be79bef1bf46,0x3f5cbf2cbf55bec4,0xbf71be163dc93f75,
0xbf13bf1dbef13f7b,0xbea13f803f7dbedb,0x3f6f3d97bdc9bf6d,0xbe89bf58bf3e3f5c,0xbf7a3efc3f223f0e,0x3f423ecf3e79bf80,0x3f31bf65bf750000,0xbf7e3e2f3eac3f4e,
0x3f51bf4abf62be48,0xbf73bcc93e163f67,0xbeb83f7f3f7fbec4,0x3f77bf09bf2cbf04,0xbe60bf5fbf463f55,0xbf273f6a3f78bd49,0x3f393ee63e95bf80,0x3dfbbf7cbf713f18,
0xbf22bef1bec43f80,0xbe953f7f3f7bbf0e,0xbdc93f753f6dbf35,0x3f62bf46bf55be48,0x3f46bf62bf6d0000,0xbf753dc93e483f55,0xbf7f3e953ec43f35,0x3ef13f223f0ebf7b,
0x3f46bf62bf6d8000,0xbf753dc93e483f55,0xbf7f3e953ec43f35,0x3ef13f223f0ebf7b,0x3f223ef13ec4bf80,0x3e95bf7fbf7b3f0e,0x3dc9bf75bf6d3f35,0xbf623f463f553e48,
0x3f6abd97bdc9bf55,0xbdfbbf51bf4e3f67,0xbf583f5f3f620000,0x3f65bcc9bd49bf5c,0xbf393f733f75be48,0x3f77be60be79bf3e,0xbe2fbf4abf463f6d,0xbf423f6f3f71be16,
0xbecf3f7f3f7fbf0e,0x3f7ebf13bf18bedb,0xbf09befcbef13f80,0xbee63f803f80bf04,0xbf31bea1be953f7b,0xbe893f7a3f78bf2c,0x3f7cbf1dbf22bec4,0xbf27beb8beac3f7d,
0xbf713e793e483f35,0x3e163f3e3f46bf75,0x3d493f4e3f55bf6d,0x3f5cbf67bf623dc9,0x3edb3f043f0ebf80,0x3f18bf80bf7f3ef1,0x3f2cbf7dbf7b3ec4,0xbf783eac3e953f22,
0x3eacbf78bf7b3f35,0xbf7d3f2c3f223e95,0xbf803f183f0e3ec4,0x3f043edb3ef1bf7f,0xbf673f5c3f558000,0x3f4e3d493dc9bf62,0x3f3e3e163e48bf6d,0x3e79bf71bf753f46,
0x3f4abcc93dc9bf55,0x3e60bf65bf713f5c,0xbf423f7c3f75bec4,0x3f6abe89be16bf2c,0xbefcbeb8bef13f7b,0xbf133f7f3f80bf18,0x3f73bf58bf460000,0xbf31bdfbbe793f67,
0xbf1d3f803f7fbf0e,0x3f7abee6beacbf04,0xbf27be2fbe953f6d,0xbecf3f773f7dbf3e,0x3f5fbf6fbf623e48,0xbf513d97bd493f4e,0x3ea13f093f22bf80,0x3f39bf7ebf783edb,
0xbe48bf0ebf353f80,0xbf553f7b3f6dbec4,0xbf7b3f553f350000,0x3f0e3e483ec4bf6d,0x3e483f0e3f35bf80,0x3f55bf7bbf6d3ec4,0x3f7bbf55bf350000,0xbf0ebe48bec43f6d,
0x3f7bbf55bf358000,0xbf0ebe48bec43f6d,0xbe48bf0ebf353f80,0xbf553f7b3f6dbec4,0xbf7b3f553f358000,0x3f0e3e483ec4bf6d,0x3e483f0e3f35bf80,0x3f55bf7bbf6d3ec4,
0xbdfb3f393f62bf7b,0x3f7abf65bf3e3e16,0xbf7f3f513f220000,0x3ecf3e893f04bf71,0x3efcbf6fbf7f3f55,0xbf7c3f273edb3e79,0x3f73bf09be95bec4,0xbcc9bf1dbf4e3f80,
0xbf7e3f313ef13e48,0x3e603ee63f2cbf7d,0xbd97bf13bf463f80,0xbf6a3f773f5cbeac,0x3f5fbeb8bdc9bf0e,0x3e2fbf42bf673f78,0xbea13f583f75bf6d,0x3f80bf4abf18bd49,
0x3f3ebf7dbf7b3f35,0xbf5c3edb3dc93ef1,0xbeacbe79bf0e3f6d,0xbf4e3f803f75bf22,0xbd493f183f55bf80,0x3f78bf71bf463e95,0x3f67bf04be48bec4,0x3e16bf2cbf623f7f,
0x3f2cbe163e48bf35,0x3f04bf67bf7f3f62,0x3f71bf78bf553ec4,0xbf183d49be953f46,0xbf803f4e3f0e8000,0x3e793eac3f22bf75,0xbedb3f5c3f7bbf6d,0x3f7dbf3ebef1bdc9,
0xbf6f3f273e953e48,0xbdfb3f133f5cbf80,0xbe60be89bf223f6d,0xbf653f803f67bf18,0x3f31bf73bf7f3f55,0xbf5f3f093e163eac,0x3f7cbf4abef10000,0xbd97becfbf3e3f78,
0x3eb8bf42bf753f7b,0xbf7e3f513f04bd49,0x3f7abf77bf463ec4,0xbee6bcc9bedb3f4e,0x3f39bea13dc9bf0e,0x3efcbf58bf7d3f71,0xbe2f3f1d3f62bf80,0x3f7fbf6abf2c3e79,
0x3e95bf22bf6d3f80,0xbf7f3f623f0ebe48,0xbef13dc9bec43f35,0xbf463f753f7bbf55,0xbf753f463ec40000,0xbdc93ef13f55bf7b,0xbf623f7f3f6dbf35,0x3f22be953e48bf0e,
0x3f75bf46bec48000,0x3dc9bef1bf553f7b,0x3f62bf7fbf6d3f35,0xbf223e95be483f0e,0x3e95bf22bf6d3f80,0xbf7f3f623f0ebe48,0xbef13dc9bec43f35,0xbf463f753f7bbf55,
0xbf7c3f7e3f46bf0e,0x3ea1bcc93f04bf3e,0xbf6a3f423e950000,0xbe893f093f67bf7d,0xbe603efc3f62bf7b,0x3f7fbf6fbf183eac,0xbf393f653f7fbf6d,0x3f4abf13bd49be79,
0xbe2fbdfbbf223f55,0xbf733f803f5cbf2c,0x3ecfbf27bf753f80,0xbf773f583edbbe16,0xbf7a3f5f3ef1be48,0xbd973eb83f4ebf71,0xbf313ee6bdc93ec4,0xbf1d3f513f80bf78,
0x3e79bd493f0ebf35,0x3f71bf7dbf623f46,0x3f18bedb3e48bec4,0x3f3ebf5cbf7f3f75,0xbf043f2c3f7bbf80,0x3f67bf4ebe953dc9,0xbe163eac3f55bf6d,0x3f80bf78bf223ef1,
0xbf783f803f55bf35,0x3eacbe163ef1bf22,0xbf4e3f673f7bbf6d,0x3f2cbf043dc9be95,0xbf5c3f3e3e488000,0xbedb3f183f75bf7f,0xbf7d3f713f0ebec4,0xbd493e793f46bf62,
0x3f7fbf7cbf223f0e,0x3cc9bdfbbf3e3f4e,0x3f77bf6fbef13ec4,0x3e60bea1bf5c3f67,0x3f65bf58be953e48,0x3ecfbefcbf713f78,0x3f4abf39bdc90000,0x3f13bf27bf7d3f80,
0xbd973e2f3f46bf55,0x3f80bf7ebf2c3f18,0xbe893eb83f62bf6d,0x3f7abf73bf043edb,0xbee63f093f75bf7b,0x3f6abf5fbeac3e79,0xbf1d3f313f7fbf80,0x3f51bf42be163d49,
0x3f803f80,0xbf80bf80,0x3f803f80,0xbf80bf80,0x3f803f80,0xbf80bf80,0x3f803f80,0xbf80bf80,
0xbf80bf8080008000,0x3f803f8080008000,0xbf80bf8080008000,0x3f803f8080008000,0xbf80bf8080008000,0x3f803f8080008000,0xbf80bf8080008000,0x3f803f8080008000,
0x3ee63f093f623f55,0xbecfbefcbf67bf5c,0x3f1d3f313f463f35,0xbf13bf27bf4ebf3e,0x3d973e2f3f7f3f7b,0xbcc9bdfbbf80bf7d,0x3e893eb83f753f6d,0xbe60bea1bf78bf71,
0xbf65bf583ef13f0e,0x3f6a3f5fbedbbf04,0xbf4abf393f223f35,0x3f513f42bf18bf2c,0xbf7fbf7c3dc93e48,0x3f803f7ebd49be16,0xbf77bf6f3e953ec4,0x3f7a3f73be79beac,
0x3f043f2c3f553f35,0xbedbbf18bf62bf46,0x3e163eac3f7b3f6d,0xbd49be79bf7fbf75,0x3f783f803e480000,0xbf71bf7dbe95bdc9,0x3f4e3f673f0e3ec4,0xbf3ebf5cbf22bef1,
0xbf5cbf3e3f0e3f35,0x3f673f4ebef1bf22,0xbf7dbf713e483ec4,0x3f803f78bdc9be95,0xbe79bd493f7b3f80,0x3eac3e16bf75bf7f,0xbf18bedb3f553f6d,0x3f2c3f04bf46bf62,
0x3e603efc3f753f55,0xbd97beb8bf7dbf67,0x3f393f653f223ec4,0xbf1dbf51bf3ebf04,0x3f7c3f7e3dc9be48,0xbf73bf80be793d49,0x3f6a3f42bef1bf35,0xbf77bf583eac3f18,
0xbf7abf5f3e953f0e,0x3f7f3f6fbe16bedb,0xbf31bee63f463f6d,0x3f4a3f13bf2cbf5c,0xbe2f3dfb3f7f3f7b,0x3ea13cc9bf78bf80,0x3ecf3f273f623f35,0xbe89bf09bf71bf4e,
0x3ef13dc9bf6dbf80,0xbf22be953f553f7b,0x3f753f46bec4bf35,0xbf7fbf623e483f0e,0x3f623f7f3ec40000,0xbf46bf75bf0ebe48,0x3e953f223f6d3f35,0xbdc9bef1bf7bbf55,
0x3f623f7f3ec48000,0xbf46bf75bf0ebe48,0x3e953f223f6d3f35,0xbdc9bef1bf7bbf55,0xbef1bdc93f6d3f80,0x3f223e95bf55bf7b,0xbf75bf463ec43f35,0x3f7f3f62be48bf0e,
0x3f393ea1bf46bf7b,0xbf5fbf093f183f67,0xbe2fbf1dbf75bf35,0xbd973ecf3f803f5c,0x3eb83f423f623f0e,0xbdfbbf13bf78bf3e,0x3f7a3f773dc9bec4,0xbf65bf80beac3e16,
0x3f313f733f223e48,0xbefcbf58bf4ebedb,0x3f7c3f4abe95bf35,0xbf7fbf6a3d493f04,0xbf6fbf273ef13f55,0x3f7e3f51be79bf2c,0xbe603e893f7f3f6d,0x3ee6bcc9bf71bf7d,
0x3f803f4ebe48bf35,0xbf78bf71bdc93ef1,0x3edb3f5c3f553ec4,0xbe16bf2cbf75bf22,0xbf3ebf7dbf0e0000,0x3f043f673f463e95,0x3eacbe79bf7bbf6d,0xbf18bd493f623f7f,
0x3d493f183f7b3f35,0x3e79beacbf7fbf62,0xbf67bf043f0e3f6d,0x3f7d3f3ebe95bf46,0x3f2c3e16bf55bf80,0xbf5cbedb3f223f75,0x3f713f783e48bec4,0xbf4ebf80bef13dc9,
0x3efc3f6f3f463e48,0xbe2fbf42bf71bf04,0x3f733f09bef1bf6d,0xbf80bf4a3e163f3e,0xbdfbbf39bf75bf0e,0xbe603ee63f803f4e,0xbf7fbf513dc93f35,0x3f6a3f773e79bedb,
0xbf5fbeb83f223f7b,0x3f7c3f27beacbf5c,0x3ea13f583f623ec4,0x3cc9bf1dbf7dbf2c,0x3f7e3f31be95bf55,0xbf7abf65bd493f18,0x3d97bf13bf7fbf35,0xbecf3e893f783f67,
0xbf55be483f353f80,0x3f7b3f0ebec4bf6d,0xbf0ebf7bbf350000,0x3e483f553f6d3ec4,0x3f553e48bf35bf80,0xbf7bbf0e3ec43f6d,0x3f0e3f7b3f350000,0xbe48bf55bf6dbec4,
0xbf0ebf7bbf358000,0x3e483f553f6d3ec4,0x3f553e48bf35bf80,0xbf7bbf0e3ec43f6d,0x3f0e3f7b3f358000,0xbe48bf55bf6dbec4,0xbf55be483f353f80,0x3f7b3f0ebec4bf6d,
0xbf5fbf6fbe953f0e,0x3f133f7f3f2cbe16,0xbea13f093f7f3f35,0x3f31bdfbbf5cbf71,0x3f1d3f803f22be48,0xbe60bf65bf67be79,0x3f27be2fbf62bf6d,0xbf6abe893f183f80,
0x3efcbeb8bf75bf55,0xbf51bd973f3e3f7d,0xbf73bf58bdc93f35,0x3f393f7e3f04beac,0xbf4abcc93f463f7b,0x3f7a3ee6bedbbf78,0x3f423f7c3ef1bec4,0xbecfbf77bf4ebd49,
0x3edbbf04bf7bbf35,0xbf4e3d493f463f75,0x3f2c3f7d3f0ebec4,0xbe79bf71bf62bdc9,0x3eac3f783f550000,0x3e16bf3ebf7fbef1,0xbf80bf183e483f6d,0x3f5c3f673e95bf22,
0x3f673f5c3e48bf35,0xbf18bf80bf223e95,0xbf3e3e163f553f6d,0x3f783eacbef1bf7f,0xbf71be793f0e3f80,0x3f7d3f2cbdc9bf62,0x3d49bf4ebf7bbec4,0xbf043edb3f753f46,
0x3f393f733ef1bf0e,0xbe89bf7abf5c3d49,0x3e2fbf4abf7fbec4,0xbf273eb83f673f4e,0xbf6abd973f223f7b,0x3f7e3f13be16bf71,0x3f583f5f3e95bf35,0xbee6bf80bf3e3e79,
0xbf313ea13f623f55,0x3f773e60bf04bf80,0x3f7c3f1dbdc9bf6d,0xbf42bf6fbedb3f18,0xbecfbf7fbf463e48,0xbdfb3f513f7d3eac,0xbf093efc3f753f35,0x3f653cc9bf2cbf78,
0x3f7f3e95bec4bf80,0xbf62bf46be483f55,0xbf223ef13f6d3f35,0x3f753dc9bf0ebf7b,0xbdc9bf75bf6d0000,0xbef13f223f7b3f0e,0x3f463f623ec4bf35,0xbe95bf7fbf553e48,
0x3dc93f753f6d8000,0x3ef1bf22bf7bbf0e,0xbf46bf62bec43f35,0x3e953f7f3f55be48,0x3f7f3e95bec4bf80,0xbf62bf46be483f55,0xbf223ef13f6d3f35,0x3f753dc9bf0ebf7b,
0xbe603f5f3f7f3e48,0x3f42becfbf5cbf3e,0x3f39bee6bf62bf35,0xbf7ebe2f3edb3f7d,0x3f513f4a3e95bf55,0xbea1bf80bf4e3eac,0xbeb8bf7fbf463ec4,0xbe893f583f803e79,
0xbf7abefc3dc93f7b,0x3f273f6a3f04bf2c,0x3f313f653ef1bf35,0xbdfbbf7cbf673e16,0xbf133f1d3f753f0e,0x3f73bcc9bf18bf71,0x3f6fbd97bf22bf6d,0xbf77bf093d493f78,
0xbf18bf67bf0e3f35,0xbd493f783f75bdc9,0x3f5c3f2c3e48bf6d,0xbeacbf7dbf463ef1,0x3e16bf71bf7b0000,0xbf3e3f043f623f22,0x3e793f803f55bec4,0x3edbbf4ebf7fbe95,
0x3f4ebedbbf55bf35,0xbf80be793e953f7f,0xbf043f3e3f7b3ec4,0x3f71be16bf22bf62,0x3f7d3eacbe48bf80,0xbf2cbf5cbef13f46,0xbf783d493f0e3f6d,0x3f673f183dc9bf75,
0x3f653f093dc9bf7b,0xbeb8bf77bf3e3f18,0xbf4abf31be953f6d,0x3e2f3f7f3f5cbedb,0x3f273f513ef1bf55,0x3cc9bf7ebf713e79,0xbefcbf6abf223f35,0xbe603f733f7dbd49,
0xbee63f583f7f3e48,0x3f6fbe89bf2cbf4e,0x3f1dbf39bf75bec4,0xbf7c3d973f043f67,0xbf423f133f623f0e,0x3f803dfbbeacbf78,0x3f5fbecfbf46bf35,0xbf7abea13e163f80,
0xbf6dbec400003f80,0x3ec43f6d3f35bf35,0x3f6d3ec40000bf80,0xbec4bf6dbf353f35,0xbf6dbec400003f80,0x3ec43f6d3f35bf35,0x3f6d3ec40000bf80,0xbec4bf6dbf353f35,
0x3ec4bf6dbf808000,0xbf6d3ec43f353f35,0xbec43f6d3f808000,0x3f6dbec4bf35bf35,0x3ec4bf6dbf808000,0xbf6d3ec43f353f35,0xbec43f6d3f808000,0x3f6dbec4bf35bf35,
0x3f7fbe2fbef1bf55,0xbf39bf1dbeac3f78,0xbf773eb83f223f35,0x3f583ee63e16bf80,0x3f733e60bdc9bf7b,0xbecfbf5fbf2c3f4e,0xbf7ebcc93e953f6d,0x3f133f423f04bf67,
0x3d973f7c3f62bf0e,0x3f31bf4abf71be79,0xbe89bf6fbf463f35,0xbf093f653f7d3d49,0xbea13f7a3f7fbe48,0x3f6abefcbf3ebf18,0x3dfbbf80bf753ec4,0xbf513f273f5c3edb,
0xbf7d3eac3f0e3f35,0x3f3e3f043e95bf7f,0x3f783d49be48bf6d,0xbedbbf4ebf223f62,0xbf183f673f7b0000,0x3f80be79bef1bf46,0x3f5cbf2cbf55bec4,0xbf71be163dc93f75,
0xbe16bf71bf553f35,0xbf2c3f5c3f753dc9,0xbe793f803f7bbec4,0x3f67bf18bf46bef1,0xbf4ebedbbe483f80,0x3d493f783f62bf22,0x3f043f3e3f0ebf6d,0x3eacbf7dbf7f3e95,
0x3f7cbdfbbe95bf55,0xbee6bf39bf183f71,0xbf6a3f273f463ec4,0x3f5f3e603d49bf78,0x3f09bf77bf7f3e48,0xbf7f3eb83f043f2c,0x3cc93f733f62bf35,0x3f4abf51bf67be16,
0xbe2f3f7e3f75bf0e,0x3f65bf31bf4ebeac,0xbecfbf42bf223f6d,0xbefc3f7a3f80be79,0x3f583e893dc9bf7b,0xbd97bf6fbf5c3f3e,0xbf803ea13ef13f35,0x3f1d3f133edbbf7d,
0x3f223ef13ec4bf80,0x3e95bf7fbf7b3f0e,0x3dc9bf75bf6d3f35,0xbf623f463f553e48,0xbf463f623f6d0000,0x3f75bdc9be48bf55,0x3f7fbe95bec4bf35,0xbef1bf22bf0e3f7b,
0xbf463f623f6d8000,0x3f75bdc9be48bf55,0x3f7fbe95bec4bf35,0xbef1bf22bf0e3f7b,0xbf22bef1bec43f80,0xbe953f7f3f7bbf0e,0xbdc93f753f6dbf35,0x3f62bf46bf55be48,
0xbeb8bf27bf223f7b,0xbf1d3f7c3f7dbeac,0x3f7abe89be95bf35,0xbea1bf31bf2c3f78,0x3f80bee6bef1bf0e,0xbefcbf09bf043f80,0xbf133f7e3f7fbec4,0x3f7fbecfbedbbf18,
0x3f6fbf42bf46be48,0xbf4abe2fbe163f71,0xbe603f773f75bf35,0x3f73bf39bf3ebe79,0xbcc93f653f62bf55,0x3f5fbf58bf5cbd49,0xbf51bdfbbdc93f6d,0xbd973f6a3f67bf4e,
0xbeac3f783f7bbf35,0x3f7dbf2cbf22be95,0x3f80bf18bf0ebec4,0xbf04bedbbef13f7f,0x3f67bf5cbf550000,0xbf4ebd49bdc93f62,0xbf3ebe16be483f6d,0xbe793f713f75bf46,
0xbf713e793e483f35,0x3e163f3e3f46bf75,0x3d493f4e3f55bf6d,0x3f5cbf67bf623dc9,0x3edb3f043f0ebf80,0x3f18bf80bf7f3ef1,0x3f2cbf7dbf7b3ec4,0xbf783eac3e953f22,
0x3f7ebf39bf22be48,0xbf09bea1bedb3f78,0xbd973f513f62bf6d,0x3f6fbf5fbf4e3d49,0xbf773ecf3e953f0e,0x3e2f3f273f3ebf7d,0x3ee6bf7abf7f3f35,0xbf803f1d3f043eac,
0x3dfb3f313f46bf7b,0x3f58bf73bf673e79,0xbf7f3f133ef13ec4,0x3eb83efc3f18bf80,0x3e89bf6abf753f55,0xbf7c3f423f2c3e16,0x3f65be60bdc9bf35,0x3cc9bf4abf5c3f71,
0xbe48bf0ebf353f80,0xbf553f7b3f6dbec4,0xbf7b3f553f350000,0x3f0e3e483ec4bf6d,0x3e483f0e3f35bf80,0x3f55bf7bbf6d3ec4,0x3f7bbf55bf350000,0xbf0ebe48bec43f6d,
0x3f7bbf55bf358000,0xbf0ebe48bec43f6d,0xbe48bf0ebf353f80,0xbf553f7b3f6dbec4,0xbf7b3f553f358000,0x3f0e3e483ec4bf6d,0x3e483f0e3f35bf80,0x3f55bf7bbf6d3ec4,
0xbf4a3f803f75bf0e,0x3f58bea1bd49bf18,0xbf423e2fbdc93f35,0xbeb83f5f3f78bf67,0x3f77bf6abf463e48,0xbf13bd97beac3f5c,0x3ee63e603ef1bf6d,0x3f31bf7ebf7d3f2c,
0xbf1dbcc9be953f55,0xbf093f733f80bf4e,0x3f27bf7cbf7f3f35,0xbf6f3efc3e793edb,0x3e893ecf3f22bf7b,0x3f51bf7fbf713f04,0xbf653f7a3f62bec4,0x3f39bdfb3e16bf3e,
0x3f2cbe163e48bf35,0x3f04bf67bf7f3f62,0x3f71bf78bf553ec4,0xbf183d49be953f46,0xbf803f4e3f0e0000,0x3e793eac3f22bf75,0xbedb3f5c3f7bbf6d,0x3f7dbf3ebef1bdc9,
0xbf3e3f7d3f7bbf35,0x3f5cbedbbdc9bef1,0x3eac3e793f0ebf6d,0x3f4ebf80bf753f22,0x3d49bf18bf553f80,0xbf783f713f46be95,0xbf673f043e483ec4,0xbe163f2c3f62bf7f,
0x3f6abf7fbf623f0e,0xbf1d3e2fbe793f2c,0x3f58befcbdc9bec4,0x3ea1bf39bf713f7d,0x3cc93ee63f46bf7b,0x3f77bf7abf4e3edb,0xbf513f7e3f75bf35,0x3f42beb83d49bf04,
0x3ecf3d973ef1bf55,0x3f4abf7cbf783f3e,0xbf093f5f3f7fbf6d,0x3f73bf31beacbe16,0xbf803f653f22be48,0x3e893e603f18bf67,0xbf133dfbbe953f35,0xbf273f6f3f80bf5c,
0xbe953f223f6dbf80,0x3f7fbf62bf0e3e48,0x3ef1bdc93ec4bf35,0x3f46bf75bf7b3f55,0x3f75bf46bec40000,0x3dc9bef1bf553f7b,0x3f62bf7fbf6d3f35,0xbf223e95be483f0e,
0xbf753f463ec48000,0xbdc93ef13f55bf7b,0xbf623f7f3f6dbf35,0x3f22be953e48bf0e,0xbe953f223f6dbf80,0x3f7fbf62bf0e3e48,0x3ef1bdc93ec4bf35,0x3f46bf75bf7b3f55,
0x3f51bf1dbdc9be48,0x3ee6bf31bf783f80,0x3eb8bd973ef1bf35,0x3f5fbf7abf713f4e,0x3f58bf77bf753f55,0xbf273ecfbe163edb,0x3f80bf73bf223ec4,0xbdfbbe2fbf2c3f5c,
0xbf133f4a3f7fbf7b,0x3f65bf39be79bd49,0xbf6f3f7f3f62bf35,0x3efcbe603eacbf18,0x3f09be893e95bf0e,0x3f42bf6abf7d3f67,0xbcc93ea13f46bf6d,0x3f7ebf7cbf3e3f04,
0x3f78bf80bf553f35,0xbeac3e16bef13f22,0x3f4ebf67bf7b3f6d,0xbf2c3f04bdc93e95,0x3f5cbf3ebe480000,0x3edbbf18bf753f7f,0x3f7dbf71bf0e3ec4,0x3d49be79bf463f62,
0x3e79bd493f0ebf35,0x3f71bf7dbf623f46,0x3f18bedb3e48bec4,0x3f3ebf5cbf7f3f75,0xbf043f2c3f7bbf80,0x3f67bf4ebe953dc9,0xbe163eac3f55bf6d,0x3f80bf78bf223ef1,
0x3f42bf51bf7f3f7b,0xbf313f1dbd493e16,0x3f5fbf6abf753f6d,0xbf093ee6be793eac,0x3f73bf7abf623f55,0xbeb83e89bedb3f04,0x3f7ebf80bf463f35,0xbe2f3d97bf183f2c,
0x3f27bf133dc9be48,0x3f39bf4abf803f7d,0x3efcbecf3e95bec4,0x3f58bf65bf783f71,0x3ea1be603ef1bf0e,0x3f6fbf77bf673f5c,0x3dfbbcc93f22bf35,0x3f7cbf7fbf4e3f3e,
0xbf353f35bf803f80,0x3f35bf3500000000,0xbf353f35bf803f80,0x3f35bf3500000000,0xbf353f35bf803f80,0x3f35bf3500000000,0xbf353f35bf803f80,0x3f35bf3500000000,
0x3f35bf3580008000,0x3f35bf353f80bf80,0x3f35bf3580008000,0x3f35bf353f80bf80,0x3f35bf3580008000,0x3f35bf353f80bf80,0x3f35bf3580008000,0x3f35bf353f80bf80,
0xbf73bf7a3f753f7b,0xbf6fbf773f713f78,0xbf7ebf803f7f3f80,0xbf7cbf7f3f7d3f80,0xbf42bf513f463f55,0xbf39bf4a3f3e3f4e,0xbf5fbf6a3f623f6d,0xbf58bf653f5c3f67,
0x3ea13e60be95be48,0x3eb83e89beacbe79,0x3dfb3cc9bdc98000,0x3e2f3d97be16bd49,0x3f273f13bf22bf0e,0x3f313f1dbf2cbf18,0x3efc3ecfbef1bec4,0x3f093ee6bf04bedb,
0xbf04bf2c3f0e3f35,0xbedbbf183ef13f22,0xbe16beac3e483ec4,0xbd49be793dc93e95,0xbf78bf803f7b3f80,0xbf71bf7d3f753f7f,0xbf4ebf673f553f6d,0xbf3ebf5c3f463f62,
0x3f5c3f3ebf55bf35,0x3f673f4ebf62bf46,0x3f7d3f71bf7bbf6d,0x3f803f78bf7fbf75,0x3e793d49be488000,0x3eac3e16be95bdc9,0x3f183edbbf0ebec4,0x3f2c3f04bf22bef1,
0x3f093e89bef1be48,0x3f273ecfbf18beac,0xbcc9bea13dc93ec4,0x3dfbbe2fbd493e79,0xbf13bf4a3f223f55,0xbee6bf313f043f3e,0xbf6fbf7f3f753f80,0xbf5fbf7a3f673f7d,
0x3f583f77bf62bf7b,0x3f423f6abf4ebf71,0x3f803f73bf7fbf6d,0x3f7e3f7cbf80bf78,0x3f513f1dbf46bf0e,0x3f653f39bf5cbf2c,0x3eb83d97be958000,0x3efc3e60bedbbe16,
0xbf62bf7f3f6d3f80,0xbf46bf753f553f7b,0xbe95bf223ec43f35,0xbdc9bef13e483f0e,0x3ef13dc9bec40000,0x3f223e95bf0ebe48,0x3f753f46bf6dbf35,0x3f7f3f62bf7bbf55,
0x3ef13dc9bec48000,0x3f223e95bf0ebe48,0x3f753f46bf6dbf35,0x3f7f3f62bf7bbf55,0x3f623f7fbf6dbf80,0x3f463f75bf55bf7b,0x3e953f22bec4bf35,0x3dc93ef1be48bf0e,
0x3cc9bee63dc93f0e,0x3e89be60be163eac,0xbf51bf7e3f623f80,0xbf27bf6f3f3e3f78,0x3f6a3f7fbf75bf7b,0x3f4a3f7cbf5cbf80,0x3f583efcbf46bec4,0x3f733f31bf67bf18,
0x3f803f65bf7fbf55,0x3f773f7abf7dbf71,0x3f133dfbbef18000,0x3f423eb8bf2cbe79,0xbecf3d973e95be48,0xbf1dbe2f3f043d49,0x3f093f5fbf22bf6d,0x3ea13f39bedbbf4e,
0x3f803f4ebf7bbf35,0x3f783f71bf7fbf62,0x3edb3f5cbf0ebf6d,0x3e163f2cbe95bf46,0xbf3ebf7d3f553f80,0xbf04bf673f223f75,0x3eacbe79be483ec4,0x3f183d49bef13dc9,
0x3d493f18be48bf35,0xbe793eac3dc9bef1,0xbf67bf043f553ec4,0xbf7dbf3e3f753f22,0x3f2c3e16bf0e8000,0x3f5c3edbbf46be95,0x3f713f78bf7bbf6d,0x3f4e3f80bf62bf7f,
0xbe893ecf3dc9bf0e,0xbf133d973edbbe79,0x3f653f7abf75bf6d,0x3f313f7ebf4ebf80,0x3f1dbcc9bef13e48,0x3f583ea1bf3ebe16,0xbf27bf7c3f463f80,0xbeb8bf5f3f043f71,
0xbf77bf6a3f7f3f55,0xbf51bf7f3f673f78,0xbee63e603e95bec4,0xbf39bdfb3f18bd49,0x3f4a3f80bf62bf7b,0x3f093f73bf2cbf7d,0x3f423e2fbf228000,0x3f6f3efcbf5cbeac,
0xbf0ebf7b3f353f80,0xbe48bf553ec43f6d,0x3f553e48bf350000,0x3f7b3f0ebf6dbec4,0x3f0e3f7bbf35bf80,0x3e483f55bec4bf6d,0xbf55be483f350000,0xbf7bbf0e3f6d3ec4,
0x3f553e48bf358000,0x3f7b3f0ebf6dbec4,0x3f0e3f7bbf35bf80,0x3e483f55bec4bf6d,0xbf55be483f358000,0xbf7bbf0e3f6d3ec4,0xbf0ebf7b3f353f80,0xbe48bf553ec43f6d,
0x3f773ecfbf62be48,0x3f7c3f42bf80bf18,0xbee6bf7a3f223f80,0xbcc9bf4a3e793f67,0xbf7ebf393f7f3f0e,0xbf58bf733f713f5c,0x3d973f51be95bf6d,0xbeb83efc3e16bf2c,
0x3e893f6abef1bf7b,0xbe2f3f27bd49bf4e,0x3f653e60bf468000,0x3f803f1dbf78bedb,0x3dfbbf313dc93f55,0x3f09bea1beac3f04,0xbf7fbf133f753ec4,0xbf6fbf5f3f7d3f3e,
0xbedb3f043e48bf35,0xbf4e3d493f22be95,0xbf2cbf7d3f553f6d,0xbe79bf713ef13f7f,0xbeacbf783f0e3f80,0x3e16bf3e3dc93f62,0x3f803f18bf7bbec4,0x3f5c3f67bf75bf46,
0xbf67bf5c3f7b3f35,0xbf18bf803f463f75,0x3f3ebe16bf0e3ec4,0x3f783eacbf62bdc9,0x3f713e79bf558000,0x3f7d3f2cbf7fbef1,0xbd493f4ebe48bf6d,0xbf043edb3e95bf22,
0xbcc9bf653e953f7b,0x3efcbf09be793f3e,0xbf513dfb3f22bec4,0xbf7fbecf3f713e16,0x3f6f3f42bf7fbf0e,0x3f1d3f7cbf4ebf67,0xbe60bf773ef13f80,0x3ea1bf31bd493f5c,
0x3f803ee6bf75be48,0x3f5f3f58bf78bf2c,0xbf13bf7e3f463f6d,0xbd97bf6a3eac3f7d,0xbeb83f273dc9bf55,0xbf4a3e2f3f18bedb,0x3f7a3e89bf628000,0x3f733f39bf80bf04,
0xbdc9bf753ec43f80,0x3ef1bf22be483f55,0x3f463f62bf6dbf35,0x3e953f7fbf0ebf7b,0xbf7fbe953f6d0000,0xbf62bf463f7b3f0e,0x3f22bef1bec43f35,0x3f753dc9bf553e48,
0x3f7f3e95bf6d8000,0x3f623f46bf7bbf0e,0xbf223ef13ec4bf35,0xbf75bdc93f55be48,0xbdc9bf753ec43f80,0x3ef1bf22be483f55,0x3f463f62bf6dbf35,0x3e953f7fbf0ebf7b,
0x3f093f77bf46bf55,0xbd973f6fbe79bf80,0x3cc9bf733e953f80,0x3f1dbf13beac3f4e,0x3f7c3dfbbf623e48,0x3f653f31bf7dbedb,0xbf6abf273f7f3ec4,0xbefcbf7a3f3e3f5c,
0xbf583e893f22bf0e,0xbf7fbeb83f783d49,0x3f803ea1bf758000,0x3f4a3f51bf71bf18,0x3e2f3f7ebef1bf7b,0xbee63f393e16bf67,0x3ecfbf42bdc93f6d,0x3f5fbe60bf2c3f04,
0xbf18bf673f553f35,0x3d49bf783e953f7f,0x3f5c3f2cbf7bbec4,0x3eac3f7dbf22bf62,0x3e16bf713e483f80,0x3f3ebf04bef13f46,0x3e793f80bf0ebf6d,0xbedb3f4e3dc9bf75,
0x3f4ebedbbf0e3f35,0x3f803e79bf753dc9,0xbf043f3e3e48bf6d,0xbf713e163f46bef1,0x3f7d3eacbf7b8000,0x3f2c3f5cbf62bf22,0xbf783d493f55bec4,0xbf67bf183f7f3e95,
0x3ea13f7abf22bf55,0xbecf3f5f3d49bf7d,0xbdfbbf803ef13f6d,0x3f13bf42be793f71,0xbd973f7cbe95bf7b,0xbf393f1d3edbbf5c,0x3e89bf6f3dc93f80,0x3f58bee6bf183f3e,
0xbf733e603f46bf0e,0xbf6abefc3f803e16,0x3f7ebcc9bf623ec4,0x3f513f27bf78beac,0xbf7fbe2f3f75be48,0xbf31bf4a3f673f04,0x3f773eb8bf7f8000,0x3f093f65bf4ebf2c,
0x3ec4bf6d00003f80,0x3f6dbec4bf353f35,0xbec43f6d0000bf80,0xbf6d3ec43f35bf35,0x3ec4bf6d00003f80,0x3f6dbec4bf353f35,0xbec43f6d0000bf80,0xbf6d3ec43f35bf35,
0x3f6d3ec4bf808000,0x3ec43f6dbf35bf35,0xbf6dbec43f808000,0xbec4bf6d3f353f35,0x3f6d3ec4bf808000,0x3ec43f6dbf35bf35,0xbf6dbec43f808000,0xbec4bf6d3f353f35,
0xbf273f513e95bf7b,0xbf803dfb3f67bf04,0x3efcbf6abdc93f80,0x3f7abea1bf4e3f2c,0xbf653f093f22bf55,0xbf6fbe893f80be16,0x3f4abf31bef13f6d,0x3f7c3d97bf783eac,
0xbf42bf133f753e48,0xbcc9bf7e3edb3f5c,0x3f5f3ecfbf7f8000,0x3e603f73bf18bf3e,0xbee6bf583f463f0e,0x3eb8bf773d493f7d,0x3f1d3f39bf62bec4,0xbe2f3f7fbe79bf71,
0x3f7dbeacbf553f35,0x3f3e3f04bf75bdc9,0xbf78bd493f7bbec4,0xbedbbf4e3f463ef1,0x3f18bf67be483f80,0x3f80be79bf623f22,0xbf5c3f2c3f0ebf6d,0xbf71be163f7fbe95,
0x3e163f71bf0ebf35,0xbf2c3f5c3e95bf7f,0x3e79bf803e483f6d,0x3f67bf18bf223f62,0x3f4e3edbbf7b8000,0x3d493f78bef1bf46,0xbf04bf3e3f553ec4,0x3eacbf7d3dc93f75,
0xbf13bf1d3f623e48,0x3ea1bf803e163f67,0x3f6f3d97bf7f3ec4,0x3e893f58bf2cbf04,0xbf7a3efc3f46bf55,0xbf42becf3f78bd49,0x3f31bf65be953f80,0x3f7ebe2fbf713f18,
0x3f51bf4abef13f7b,0x3f733cc9bf7d3edb,0xbeb83f7fbdc9bf6d,0xbf773f093f3ebf5c,0xbe60bf5f3f223f0e,0x3f27bf6abe793f80,0x3f393ee6bf758000,0xbdfb3f7cbeacbf4e,
0x3f46bf62bec43f80,0x3f75bdc9bf7b3f0e,0xbf7f3e953f6dbf35,0xbef1bf223f553e48,0x3f223ef1bf6d0000,0xbe953f7fbe48bf55,0x3dc9bf753ec43f35,0x3f62bf46bf0e3f7b,
0x3f223ef1bf6d8000,0xbe953f7fbe48bf55,0x3dc9bf753ec43f35,0x3f62bf46bf0e3f7b,0xbf463f623ec4bf80,0xbf753dc93f7bbf0e,0x3f7fbe95bf6d3f35,0x3ef13f22bf55be48,
0xbf6a3d973f7fbf0e,0xbdfbbf513f183edb,0x3f58bf5fbef13f80,0x3f65bcc9bf803f04,0x3f39bf73be953f7b,0x3f77be60bf783f2c,0x3e2f3f4abf22bec4,0xbf423f6f3eacbf7d,
0x3ecfbf7f3dc93f55,0x3f7ebf13bf4e3f67,0x3f093efcbf628000,0xbee63f80bd49bf5c,0x3f313ea1bf753e48,0xbe893f7abe79bf3e,0xbf7c3f1d3f46bf6d,0xbf27beb83f71be16,
0xbeac3f78be48bf35,0xbf7d3f2c3f46bf75,0x3f80bf18bf553f6d,0x3f043edbbf623dc9,0x3f67bf5cbf0e3f80,0x3f4e3d49bf7f3ef1,0xbf3ebe163f7bbec4,0x3e79bf713e953f22,
0xbf713e793f7bbf35,0xbe16bf3e3f223e95,0x3d493f4ebf0ebec4,0xbf5c3f673ef1bf7f,0x3edb3f04bf558000,0xbf183f803dc9bf62,0x3f2cbf7dbe483f6d,0x3f78beacbf753f46,
0x3f4abcc9bf7f3f0e,0xbe603f65beacbf04,0xbf423f7c3e95bf6d,0xbf6a3e893f7dbf3e,0xbefcbeb83f62be48,0x3f13bf7fbd493f4e,0x3f73bf58bf223f80,0x3f313dfbbf783edb,
0xbf1d3f803dc9bf55,0xbf7a3ee63f71bf5c,0xbf27be2f3f75bec4,0x3ecfbf773e163f2c,0x3f5fbf6fbef13f7b,0x3f51bd97bf803f18,0x3ea13f09bf468000,0xbf393f7e3e79bf67,
0x3f7bbf55bf353f80,0x3f0e3e48bf6d3ec4,0xbe48bf0e3f350000,0x3f55bf7bbec43f6d,0xbf7b3f553f35bf80,0xbf0ebe483f6dbec4,0x3e483f0ebf350000,0xbf553f7b3ec4bf6d,
0x3e483f0ebf358000,0xbf553f7b3ec4bf6d,0x3f7bbf55bf353f80,0x3f0e3e48bf6d3ec4,0xbe48bf0e3f358000,0x3f55bf7bbec43f6d,0xbf7b3f553f35bf80,0xbf0ebe483f6dbec4,
0x3dfbbf393ef13e48,0x3f7abf65bf2c3f7d,0x3f7fbf51bf463f80,0x3ecf3e89bf5c3eac,0xbefc3f6fbdc9bf0e,0xbf7c3f273f67bf78,0xbf733f093f75bf6d,0xbcc9bf1d3f183d49,
0x3f7ebf31bf623f7b,0x3e603ee6bf3e3e16,0x3d973f13bf228000,0xbf6a3f773f04bf71,0xbf5f3eb83f7fbf55,0x3e2fbf423edb3e79,0x3ea1bf583e953ec4,0x3f80bf4abf4e3f80,
0xbf2c3e163f7bbf35,0x3f04bf673dc93ef1,0xbf713f783f0ebf6d,0xbf183d493f75bf22,0x3f80bf4ebf553f80,0x3e793eacbf463e95,0x3edbbf5c3e483ec4,0x3f7dbf3ebf623f7f,
0x3f3ebf7dbe483f35,0x3f5cbedbbf7f3f62,0xbeacbe793f55bec4,0x3f4ebf80be953f46,0xbd493f18bf0e8000,0xbf783f713f22bf75,0x3f67bf04bf7b3f6d,0xbe163f2cbef1bdc9,
0xbf6f3f273f75bf7b,0x3dfbbf133f04bd49,0xbe60be893f46bec4,0x3f65bf80bedb3f4e,0x3f31bf73bdc93f0e,0x3f5fbf09bf7d3f71,0x3f7cbf4abf623f80,0x3d973ecfbf2c3e79,
0x3eb8bf423e953e48,0x3f7ebf51bf5c3f80,0x3f7abf77bf223f6d,0x3ee63cc9bf673f18,0x3f39bea1bf7f3f55,0xbefc3f58be16beac,0xbe2f3f1dbef18000,0xbf7f3f6a3f3ebf78,
0x3f75bf46bf6d3f80,0xbdc93ef1bf0e3e48,0x3f62bf7fbec43f35,0x3f22be95bf7b3f55,0x3e95bf223ec40000,0x3f7fbf62bf553f7b,0xbef13dc93f6dbf35,0x3f46bf75be483f0e,
0xbe953f22bec48000,0xbf7f3f623f55bf7b,0x3ef1bdc9bf6d3f35,0xbf463f753e48bf0e,0x3f75bf46bf6d3f80,0xbdc93ef1bf0e3e48,0x3f62bf7fbec43f35,0x3f22be95bf7b3f55,
0x3f7cbf7ebf223f55,0x3ea1bcc9bf5c3f2c,0x3f6abf42bf753f80,0xbe893f09bedb3e16,0x3e60befc3ef1be48,0x3f7fbf6fbf4e3f71,0x3f39bf65bdc93ec4,0x3f4abf13bf803f78,
0x3e2f3dfbbf463f0e,0xbf733f803f04bf3e,0xbecf3f27be958000,0xbf773f583f67bf7d,0x3f7abf5fbf623f7b,0xbd973eb8bf183eac,0x3f31bee6bf7f3f6d,0xbf1d3f51bd49be79,
0x3f78bf80bf0e3f35,0x3eacbe16bf623f46,0x3f4ebf67be483ec4,0x3f2cbf04bf7f3f75,0x3f5cbf3ebf7b3f80,0xbedb3f18be953dc9,0x3f7dbf71bf553f6d,0xbd493e79bf223ef1,
0x3e79bd49bf553f35,0xbf713f7d3ef1bf22,0x3f18bedbbf7b3f6d,0xbf3e3f5c3dc9be95,0xbf043f2cbe488000,0xbf673f4e3f75bf7f,0xbe163eacbf0e3ec4,0xbf803f783f46bf62,
0x3f7fbf7cbf463f55,0xbcc93dfbbf2c3f18,0x3f77bf6fbf623f6d,0xbe603ea1bf043edb,0x3f65bf58bf753f7b,0xbecf3efcbeac3e79,0x3f4abf39bf7f3f80,0xbf133f27be163d49,
0xbd973e2fbf223f0e,0xbf803f7e3f3ebf4e,0xbe893eb8bef13ec4,0xbf7a3f733f5cbf67,0xbee63f09be953e48,0xbf6a3f5f3f71bf78,0xbf1d3f31bdc98000,0xbf513f423f7dbf80,
0xbf353f35bf803f80,0x3f35bf3500000000,0xbf353f35bf803f80,0x3f35bf3500000000,0xbf353f35bf803f80,0x3f35bf3500000000,0xbf353f35bf803f80,0x3f35bf3500000000,
0x3f35bf3580008000,0x3f35bf353f80bf80,0x3f35bf3580008000,0x3f35bf353f80bf80,0x3f35bf3580008000,0x3f35bf353f80bf80,0x3f35bf3580008000,0x3f35bf353f80bf80,
0xbee6bf093ef13f0e,0xbecfbefc3edb3f04,0xbf1dbf313f223f35,0xbf13bf273f183f2c,0xbd97be2f3dc93e48,0xbcc9bdfb3d493e16,0xbe89beb83e953ec4,0xbe60bea13e793eac,
0x3f653f58bf62bf55,0x3f6a3f5fbf67bf5c,0x3f4a3f39bf46bf35,0x3f513f42bf4ebf3e,0x3f7f3f7cbf7fbf7b,0x3f803f7ebf80bf7d,0x3f773f6fbf75bf6d,0x3f7a3f73bf78bf71,
0x3f5c3f3ebf55bf35,0x3f673f4ebf62bf46,0x3f7d3f71bf7bbf6d,0x3f803f78bf7fbf75,0x3e793d49be480000,0x3eac3e16be95bdc9,0x3f183edbbf0ebec4,0x3f2c3f04bf22bef1,
0x3f043f2cbf0ebf35,0x3edb3f18bef1bf22,0x3e163eacbe48bec4,0x3d493e79bdc9be95,0x3f783f80bf7bbf80,0x3f713f7dbf75bf7f,0x3f4e3f67bf55bf6d,0x3f3e3f5cbf46bf62,
0x3e603efcbe95bf0e,0x3d973eb8be16bedb,0x3f393f65bf46bf6d,0x3f1d3f51bf2cbf5c,0x3f7c3f7ebf7fbf7b,0x3f733f80bf78bf80,0x3f6a3f42bf62bf35,0x3f773f58bf71bf4e,
0xbf7abf5f3f753f55,0xbf7fbf6f3f7d3f67,0xbf31bee63f223ec4,0xbf4abf133f3e3f04,0xbe2f3dfb3dc9be48,0xbea1bcc93e79bd49,0x3ecf3f27bef1bf35,0x3e893f09beacbf18,
0x3f623f7fbf6dbf80,0x3f463f75bf55bf7b,0x3e953f22bec4bf35,0x3dc93ef1be48bf0e,0xbef1bdc93ec40000,0xbf22be953f0e3e48,0xbf75bf463f6d3f35,0xbf7fbf623f7b3f55,
0xbef1bdc93ec48000,0xbf22be953f0e3e48,0xbf75bf463f6d3f35,0xbf7fbf623f7b3f55,0xbf62bf7f3f6d3f80,0xbf46bf753f553f7b,0xbe95bf223ec43f35,0xbdc9bef13e483f0e,
0xbf39bea13f223e48,0xbf5fbf093f4e3edb,0x3e2f3f1dbe95bf35,0xbd973ecfbd49bf04,0xbeb8bf423ef13f55,0xbdfbbf133e793f2c,0xbf7abf773f7f3f6d,0xbf65bf803f713f7d,
0xbf31bf733f463f7b,0xbefcbf583f183f67,0xbf7cbf4a3f753f35,0xbf7fbf6a3f803f5c,0x3f6f3f27bf62bf0e,0x3f7e3f51bf78bf3e,0x3e60be89bdc93ec4,0x3ee6bcc9beac3e16,
0xbd49bf183e483f35,0x3e79beacbdc93ef1,0x3f673f04bf55bec4,0x3f7d3f3ebf75bf22,0xbf2cbe163f0e0000,0xbf5cbedb3f463e95,0xbf71bf783f7b3f6d,0xbf4ebf803f623f7f,
0x3f803f4ebf7bbf35,0x3f783f71bf7fbf62,0x3edb3f5cbf0ebf6d,0x3e163f2cbe95bf46,0xbf3ebf7d3f553f80,0xbf04bf673f223f75,0x3eacbe79be483ec4,0x3f183d49bef13dc9,
0x3efc3f6fbf22bf7b,0x3e2f3f42beacbf5c,0x3f733f09bf62bec4,0x3f803f4abf7dbf2c,0xbdfbbf393e953f55,0x3e60bee6bd493f18,0xbf7fbf513f7f3f35,0xbf6abf773f783f67,
0xbf5fbeb83f463e48,0xbf7cbf273f713f04,0x3ea13f58bef1bf6d,0xbcc93f1dbe16bf3e,0x3f7e3f31bf75bf0e,0x3f7a3f65bf80bf4e,0x3d97bf133dc93f35,0x3ecfbe89be793edb,
0xbf0ebf7b3f353f80,0xbe48bf553ec43f6d,0x3f553e48bf350000,0x3f7b3f0ebf6dbec4,0x3f0e3f7bbf35bf80,0x3e483f55bec4bf6d,0xbf55be483f350000,0xbf7bbf0e3f6d3ec4,
0x3f553e48bf358000,0x3f7b3f0ebf6dbec4,0x3f0e3f7bbf35bf80,0x3e483f55bec4bf6d,0xbf55be483f358000,0xbf7bbf0e3f6d3ec4,0xbf0ebf7b3f353f80,0xbe48bf553ec43f6d,
0x3f5f3f6fbf75bf55,0x3f133f7fbf3ebf7d,0x3ea1bf09bdc93f35,0x3f31bdfbbf043eac,0xbf1dbf803f463f7b,0xbe60bf653edb3f78,0xbf273e2f3ef1bec4,0xbf6abe893f4e3d49,
0xbefc3eb83e95bf0e,0xbf51bd973f2cbe16,0x3f733f58bf7fbf35,0x3f393f7ebf5cbf71,0x3f4a3cc9bf223e48,0x3f7a3ee6bf67be79,0xbf42bf7c3f623f6d,0xbecfbf773f183f80,
0xbf67bf5c3f7b3f35,0xbf18bf803f463f75,0x3f3ebe16bf0e3ec4,0x3f783eacbf62bdc9,0x3f713e79bf550000,0x3f7d3f2cbf7fbef1,0xbd493f4ebe48bf6d,0xbf043edb3e95bf22,
0x3edbbf04be483f35,0x3f4ebd49bf223e95,0x3f2c3f7dbf55bf6d,0x3e793f71bef1bf7f,0x3eac3f78bf0ebf80,0xbe163f3ebdc9bf62,0xbf80bf183f7b3ec4,0xbf5cbf673f753f46,
0x3f393f73bf62bf55,0x3e893f7abf04bf80,0x3e2fbf4a3dc93f6d,0x3f27beb8bedb3f18,0xbf6abd973f46be48,0xbf7ebf133f7d3eac,0x3f583f5fbf75bf35,0x3ee63f80bf2cbf78,
0xbf313ea13ef1bf0e,0xbf77be603f5cbd49,0x3f7c3f1dbf7fbec4,0x3f423f6fbf67bf4e,0xbecfbf7f3f223f7b,0x3dfbbf513e163f71,0xbf093efc3e95bf35,0xbf65bcc93f3ebe79,
0x3dc93f75bec4bf80,0xbef13f223e48bf55,0xbf46bf623f6d3f35,0xbe95bf7f3f0e3f7b,0x3f7f3e95bf6d0000,0x3f623f46bf7bbf0e,0xbf223ef13ec4bf35,0xbf75bdc93f55be48,
0xbf7fbe953f6d8000,0xbf62bf463f7b3f0e,0x3f22bef1bec43f35,0x3f753dc9bf553e48,0x3dc93f75bec4bf80,0xbef13f223e48bf55,0xbf46bf623f6d3f35,0xbe95bf7f3f0e3f7b,
0x3e60bf5f3dc93f7b,0x3f42becfbf043f2c,0xbf393ee63ef1bf35,0xbf7ebe2f3f67be16,0xbf51bf4a3f753f0e,0xbea1bf803f183f71,0x3eb83f7fbf22bf6d,0xbe893f58bd49bf78,
0x3f7a3efcbf7fbe48,0x3f273f6abf5cbf3e,0xbf31bf653f623f35,0xbdfbbf7c3edb3f7d,0x3f13bf1dbe953f55,0x3f73bcc9bf4e3eac,0xbf6f3d973f46bec4,0xbf77bf093f803e79,
0xbf4e3edb3f0ebf35,0xbf80be793f75bdc9,0x3f04bf3ebe483f6d,0x3f71be16bf463ef1,0xbf7dbeac3f7b0000,0xbf2cbf5c3f623f22,0x3f78bd49bf553ec4,0x3f673f18bf7fbe95,
0xbf18bf673f553f35,0x3d49bf783e953f7f,0x3f5c3f2cbf7bbec4,0x3eac3f7dbf22bf62,0x3e16bf713e483f80,0x3f3ebf04bef13f46,0x3e793f80bf0ebf6d,0xbedb3f4e3dc9bf75,
0x3f653f09bf7fbe48,0x3eb83f77bf2cbf4e,0xbf4abf313f753ec4,0xbe2fbf7f3f043f67,0x3f273f51bf62bf0e,0xbcc93f7ebeacbf78,0xbefcbf6a3f463f35,0x3e60bf733e163f80,
0xbee63f583dc9bf7b,0xbf6f3e893f3ebf18,0x3f1dbf39be953f6d,0x3f7cbd97bf5c3edb,0xbf423f133ef1bf55,0xbf80bdfb3f71be79,0x3f5fbecfbf223f35,0x3f7a3ea1bf7d3d49,
0x3ec4bf6d00003f80,0x3f6dbec4bf353f35,0xbec43f6d0000bf80,0xbf6d3ec43f35bf35,0x3ec4bf6d00003f80,0x3f6dbec4bf353f35,0xbec43f6d0000bf80,0xbf6d3ec43f35bf35,
0x3f6d3ec4bf808000,0x3ec43f6dbf35bf35,0xbf6dbec43f808000,0xbec4bf6d3f353f35,0x3f6d3ec4bf808000,0x3ec43f6dbf35bf35,0xbf6dbec43f808000,0xbec4bf6d3f353f35,
0xbf7f3e2f3f62bf0e,0xbf39bf1d3f713e79,0x3f77beb8bf463f35,0x3f583ee6bf7dbd49,0xbf73be603f7fbe48,0xbecfbf5f3f3e3f18,0x3f7e3cc9bf753ec4,0x3f133f42bf5cbedb,
0xbd97bf7c3ef13f55,0x3f31bf4abeac3f78,0x3e893f6fbf22bf35,0xbf093f653e16bf80,0x3ea1bf7a3dc93f7b,0x3f6abefcbf2c3f4e,0xbdfb3f80be95bf6d,0xbf513f273f04bf67,
0x3e163f71bf0ebf35,0xbf2c3f5c3e95bf7f,0x3e79bf803e483f6d,0x3f67bf18bf223f62,0x3f4e3edbbf7b0000,0x3d493f78bef1bf46,0xbf04bf3e3f553ec4,0x3eacbf7d3dc93f75,
0xbf7d3eac3f55bf35,0xbf3ebf043f753dc9,0x3f783d49bf7b3ec4,0x3edb3f4ebf46bef1,0xbf183f673e48bf80,0xbf803e793f62bf22,0x3f5cbf2cbf0e3f6d,0x3f713e16bf7f3e95,
0x3f7cbdfbbf753f0e,0x3ee63f39bf4ebeac,0xbf6a3f273f22bf6d,0xbf5fbe603f80be79,0x3f09bf77bdc93f7b,0x3f7fbeb8bf5c3f3e,0x3cc93f73bef1bf35,0xbf4a3f513edbbf7d,
0xbe2f3f7ebe95bf55,0xbf653f313f18bf71,0xbecfbf423f463ec4,0x3efcbf7abd493f78,0x3f583e89bf7f3e48,0x3d973f6fbf04bf2c,0xbf803ea13f62bf35,0xbf1dbf133f673e16,
0xbf463f623ec4bf80,0xbf753dc93f7bbf0e,0x3f7fbe95bf6d3f35,0x3ef13f22bf55be48,0xbf22bef13f6d0000,0x3e95bf7f3e483f55,0xbdc93f75bec4bf35,0xbf623f463f0ebf7b,
0xbf22bef13f6d8000,0x3e95bf7f3e483f55,0xbdc93f75bec4bf35,0xbf623f463f0ebf7b,0x3f46bf62bec43f80,0x3f75bdc9bf7b3f0e,0xbf7f3e953f6dbf35,0xbef1bf223f553e48,
0x3eb83f27bf46be48,0xbf1d3f7c3e16bf71,0xbf7a3e893f75bf35,0xbea1bf313f3e3e79,0xbf803ee63f62bf55,0xbefcbf093f5c3d49,0x3f13bf7ebdc93f6d,0x3f7fbecfbf673f4e,
0xbf6f3f423f22bf7b,0xbf4abe2f3f7dbeac,0x3e60bf773e953f35,0x3f73bf39bf2c3f78,0x3cc9bf653ef13f0e,0x3f5fbf58bf043f80,0x3f513dfbbf7f3ec4,0xbd973f6abedbbf18,
0x3f71be79bf7b3f35,0x3e163f3ebf22be95,0xbd49bf4e3f0e3ec4,0x3f5cbf67bef13f7f,0xbedbbf043f550000,0x3f18bf80bdc93f62,0xbf2c3f7d3e48bf6d,0xbf783eac3f75bf46,
0xbeac3f78be48bf35,0xbf7d3f2c3f46bf75,0x3f80bf18bf553f6d,0x3f043edbbf623dc9,0x3f67bf5cbf0e3f80,0x3f4e3d49bf7f3ef1,0xbf3ebe163f7bbec4,0x3e79bf713e953f22,
0x3f7ebf39bf463f7b,0x3f093ea1bf673e79,0xbd973f51bef1bec4,0xbf6f3f5f3f18bf80,0xbf773ecf3f75bf55,0xbe2fbf273f2c3e16,0x3ee6bf7a3dc93f35,0x3f80bf1dbf5c3f71,
0x3dfb3f31bf22be48,0xbf583f733edbbf78,0xbf7f3f133f62bf6d,0xbeb8befc3f4ebd49,0x3e89bf6a3e953f0e,0x3f7cbf42bf3e3f7d,0x3f65be60bf7f3f35,0xbcc93f4abf04beac,
0x3f7bbf55bf353f80,0x3f0e3e48bf6d3ec4,0xbe48bf0e3f350000,0x3f55bf7bbec43f6d,0xbf7b3f553f35bf80,0xbf0ebe483f6dbec4,0x3e483f0ebf350000,0xbf553f7b3ec4bf6d,
0x3e483f0ebf358000,0xbf553f7b3ec4bf6d,0x3f7bbf55bf353f80,0x3f0e3e48bf6d3ec4,0xbe48bf0e3f358000,0x3f55bf7bbec43f6d,0xbf7b3f553f35bf80,0xbf0ebe483f6dbec4,
0x3f4abf80be953f55,0x3f58bea1bf803f4e,0x3f42be2fbf7f3f35,0xbeb83f5fbe79bedb,0xbf773f6a3f22bf7b,0xbf13bd973f71bf04,0xbee6be603f62bec4,0x3f31bf7ebe163f3e,
0x3f1d3cc9bf753f0e,0xbf093f73bd49bf18,0xbf273f7c3dc9bf35,0xbf6f3efc3f78bf67,0xbe89becf3f46be48,0x3f51bf7fbeac3f5c,0x3f65bf7abef13f6d,0x3f39bdfbbf7d3f2c,
0x3f3ebf7dbe483f35,0x3f5cbedbbf7f3f62,0xbeacbe793f55bec4,0x3f4ebf80be953f46,0xbd493f18bf0e0000,0xbf783f713f22bf75,0x3f67bf04bf7b3f6d,0xbe163f2cbef1bdc9,
0x3f2cbe16bf7b3f35,0xbf043f67bdc9bef1,0x3f71bf78bf0e3f6d,0x3f18bd49bf753f22,0xbf803f4e3f55bf80,0xbe79beac3f46be95,0xbedb3f5cbe48bec4,0xbf7d3f3e3f62bf7f,
0x3f6abf7fbef13f55,0x3f1dbe2fbf783f3e,0x3f58befcbf7f3f6d,0xbea13f39beacbe16,0x3cc93ee6bf223e48,0xbf773f7a3f18bf67,0xbf513f7e3e95bf35,0xbf423eb83f80bf5c,
0x3ecf3d97bf623f0e,0xbf4a3f7c3e79bf2c,0xbf093f5fbdc9bec4,0xbf733f313f71bf7d,0xbf803f653f46bf7b,0xbe89be603f4ebedb,0xbf133dfb3f75bf35,0x3f27bf6fbd493f04,
0xbf753f463f6dbf80,0x3dc9bef13f0ebe48,0xbf623f7f3ec4bf35,0xbf223e953f7bbf55,0xbe953f22bec40000,0xbf7f3f623f55bf7b,0x3ef1bdc9bf6d3f35,0xbf463f753e48bf0e,
0x3e95bf223ec48000,0x3f7fbf62bf553f7b,0xbef13dc93f6dbf35,0x3f46bf75be483f0e,0xbf753f463f6dbf80,0x3dc9bef13f0ebe48,0xbf623f7f3ec4bf35,0xbf223e953f7bbf55,
0xbf513f1d3f7fbf7b,0x3ee6bf313e793d49,0xbeb83d973f62bf35,0x3f5fbf7abeac3f18,0xbf583f773e95bf0e,0xbf273ecf3f7dbf67,0xbf803f733f46bf6d,0xbdfbbe2f3f3ebf04,
0x3f13bf4a3dc93e48,0x3f65bf39bf783f80,0x3f6fbf7fbef13f35,0x3efcbe60bf713f4e,0xbf093e893f75bf55,0x3f42bf6abe163edb,0x3cc9bea13f22bec4,0x3f7ebf7cbf2c3f5c,
0xbe793d493f55bf35,0x3f71bf7dbef13f22,0xbf183edb3f7bbf6d,0x3f3ebf5cbdc93e95,0x3f04bf2c3e480000,0x3f67bf4ebf753f7f,0x3e16beac3f0ebec4,0x3f80bf78bf463f62,
0x3f78bf80bf0e3f35,0x3eacbe16bf623f46,0x3f4ebf67be483ec4,0x3f2cbf04bf7f3f75,0x3f5cbf3ebf7b3f80,0xbedb3f18be953dc9,0x3f7dbf71bf553f6d,0xbd493e79bf223ef1,
0x3f42bf51bdc93e48,0x3f31bf1dbf803f7d,0x3f5fbf6abe953ec4,0x3f09bee6bf783f71,0x3f73bf7abef13f0e,0x3eb8be89bf673f5c,0x3f7ebf80bf223f35,0x3e2fbd97bf4e3f3e,
0x3f27bf13bf7f3f7b,0xbf393f4a3d49be16,0x3efcbecfbf753f6d,0xbf583f653e79beac,0x3ea1be60bf623f55,0xbf6f3f773edbbf04,0x3dfbbcc9bf463f35,0xbf7c3f7f3f18bf2c,
0xbf353f35bf803f80,0x3f35bf3500000000,0xbf353f35bf803f80,0x3f35bf3500000000,0xbf353f35bf803f80,0x3f35bf3500000000,0xbf353f35bf803f80,0x3f35bf3500000000,
0x3f35bf3580008000,0x3f35bf353f80bf80,0x3f35bf3580008000,0x3f35bf353f80bf80,0x3f35bf3580008000,0x3f35bf353f80bf80,0x3f35bf3580008000,0x3f35bf353f80bf80,
0x3ea13e60be95be48,0x3eb83e89beacbe79,0x3dfb3cc9bdc90000,0x3e2f3d97be16bd49,0x3f273f13bf22bf0e,0x3f313f1dbf2cbf18,0x3efc3ecfbef1bec4,0x3f093ee6bf04bedb,
0x3f733f7abf75bf7b,0x3f6f3f77bf71bf78,0x3f7e3f80bf7fbf80,0x3f7c3f7fbf7dbf80,0x3f423f51bf46bf55,0x3f393f4abf3ebf4e,0x3f5f3f6abf62bf6d,0x3f583f65bf5cbf67,
0x3f043f2cbf0ebf35,0x3edb3f18bef1bf22,0x3e163eacbe48bec4,0x3d493e79bdc9be95,0x3f783f80bf7bbf80,0x3f713f7dbf75bf7f,0x3f4e3f67bf55bf6d,0x3f3e3f5cbf46bf62,
0xbf5cbf3e3f553f35,0xbf67bf4e3f623f46,0xbf7dbf713f7b3f6d,0xbf80bf783f7f3f75,0xbe79bd493e488000,0xbeacbe163e953dc9,0xbf18bedb3f0e3ec4,0xbf2cbf043f223ef1,
0xbf58bf773f623f7b,0xbf42bf6a3f4e3f71,0xbf80bf733f7f3f6d,0xbf7ebf7c3f803f78,0xbf51bf1d3f463f0e,0xbf65bf393f5c3f2c,0xbeb8bd973e950000,0xbefcbe603edb3e16,
0x3f093e89bef1be48,0x3f273ecfbf18beac,0xbcc9bea13dc93ec4,0x3dfbbe2fbd493e79,0xbf13bf4a3f223f55,0xbee6bf313f043f3e,0xbf6fbf7f3f753f80,0xbf5fbf7a3f673f7d,
0xbf62bf7f3f6d3f80,0xbf46bf753f553f7b,0xbe95bf223ec43f35,0xbdc9bef13e483f0e,0x3ef13dc9bec40000,0x3f223e95bf0ebe48,0x3f753f46bf6dbf35,0x3f7f3f62bf7bbf55,
0x3ef13dc9bec48000,0x3f223e95bf0ebe48,0x3f753f46bf6dbf35,0x3f7f3f62bf7bbf55,0x3f623f7fbf6dbf80,0x3f463f75bf55bf7b,0x3e953f22bec4bf35,0x3dc93ef1be48bf0e,
0x3f803f65bf7fbf55,0x3f773f7abf7dbf71,0x3f133dfbbef10000,0x3f423eb8bf2cbe79,0xbecf3d973e95be48,0xbf1dbe2f3f043d49,0x3f093f5fbf22bf6d,0x3ea13f39bedbbf4e,
0xbcc93ee6bdc9bf0e,0xbe893e603e16beac,0x3f513f7ebf62bf80,0x3f273f6fbf3ebf78,0xbf6abf7f3f753f7b,0xbf4abf7c3f5c3f80,0xbf58befc3f463ec4,0xbf73bf313f673f18,
0xbf80bf4e3f7b3f35,0xbf78bf713f7f3f62,0xbedbbf5c3f0e3f6d,0xbe16bf2c3e953f46,0x3f3e3f7dbf55bf80,0x3f043f67bf22bf75,0xbeac3e793e48bec4,0xbf18bd493ef1bdc9,
0xbd49bf183e483f35,0x3e79beacbdc93ef1,0x3f673f04bf55bec4,0x3f7d3f3ebf75bf22,0xbf2cbe163f0e8000,0xbf5cbedb3f463e95,0xbf71bf783f7b3f6d,0xbf4ebf803f623f7f,
0x3f773f6abf7fbf55,0x3f513f7fbf67bf78,0x3ee6be60be953ec4,0x3f393dfbbf183d49,0xbf4abf803f623f7b,0xbf09bf733f2c3f7d,0xbf42be2f3f220000,0xbf6fbefc3f5c3eac,
0xbe893ecf3dc9bf0e,0xbf133d973edbbe79,0x3f653f7abf75bf6d,0x3f313f7ebf4ebf80,0x3f1dbcc9bef13e48,0x3f583ea1bf3ebe16,0xbf27bf7c3f463f80,0xbeb8bf5f3f043f71,
0xbf0ebf7b3f353f80,0xbe48bf553ec43f6d,0x3f553e48bf350000,0x3f7b3f0ebf6dbec4,0x3f0e3f7bbf35bf80,0x3e483f55bec4bf6d,0xbf55be483f350000,0xbf7bbf0e3f6d3ec4,
0x3f553e48bf358000,0x3f7b3f0ebf6dbec4,0x3f0e3f7bbf35bf80,0x3e483f55bec4bf6d,0xbf55be483f358000,0xbf7bbf0e3f6d3ec4,0xbf0ebf7b3f353f80,0xbe48bf553ec43f6d,
0x3e893f6abef1bf7b,0xbe2f3f27bd49bf4e,0x3f653e60bf460000,0x3f803f1dbf78bedb,0x3dfbbf313dc93f55,0x3f09bea1beac3f04,0xbf7fbf133f753ec4,0xbf6fbf5f3f7d3f3e,
0xbf77becf3f623e48,0xbf7cbf423f803f18,0x3ee63f7abf22bf80,0x3cc93f4abe79bf67,0x3f7e3f39bf7fbf0e,0x3f583f73bf71bf5c,0xbd97bf513e953f6d,0x3eb8befcbe163f2c,
0x3edbbf04be483f35,0x3f4ebd49bf223e95,0x3f2c3f7dbf55bf6d,0x3e793f71bef1bf7f,0x3eac3f78bf0ebf80,0xbe163f3ebdc9bf62,0xbf80bf183f7b3ec4,0xbf5cbf673f753f46,
0x3f673f5cbf7bbf35,0x3f183f80bf46bf75,0xbf3e3e163f0ebec4,0xbf78beac3f623dc9,0xbf71be793f558000,0xbf7dbf2c3f7f3ef1,0x3d49bf4e3e483f6d,0x3f04bedbbe953f22,
0xbf80bee63f753e48,0xbf5fbf583f783f2c,0x3f133f7ebf46bf6d,0x3d973f6abeacbf7d,0x3eb8bf27bdc93f55,0x3f4abe2fbf183edb,0xbf7abe893f620000,0xbf73bf393f803f04,
0xbcc9bf653e953f7b,0x3efcbf09be793f3e,0xbf513dfb3f22bec4,0xbf7fbecf3f713e16,0x3f6f3f42bf7fbf0e,0x3f1d3f7cbf4ebf67,0xbe60bf773ef13f80,0x3ea1bf31bd493f5c,
0xbdc9bf753ec43f80,0x3ef1bf22be483f55,0x3f463f62bf6dbf35,0x3e953f7fbf0ebf7b,0xbf7fbe953f6d0000,0xbf62bf463f7b3f0e,0x3f22bef1bec43f35,0x3f753dc9bf553e48,
0x3f7f3e95bf6d8000,0x3f623f46bf7bbf0e,0xbf223ef13ec4bf35,0xbf75bdc93f55be48,0xbdc9bf753ec43f80,0x3ef1bf22be483f55,0x3f463f62bf6dbf35,0x3e953f7fbf0ebf7b,
0xbf583e893f22bf0e,0xbf7fbeb83f783d49,0x3f803ea1bf750000,0x3f4a3f51bf71bf18,0x3e2f3f7ebef1bf7b,0xbee63f393e16bf67,0x3ecfbf42bdc93f6d,0x3f5fbe60bf2c3f04,
0xbf09bf773f463f55,0x3d97bf6f3e793f80,0xbcc93f73be95bf80,0xbf1d3f133eacbf4e,0xbf7cbdfb3f62be48,0xbf65bf313f7d3edb,0x3f6a3f27bf7fbec4,0x3efc3f7abf3ebf5c,
0x3f183f67bf55bf35,0xbd493f78be95bf7f,0xbf5cbf2c3f7b3ec4,0xbeacbf7d3f223f62,0xbe163f71be48bf80,0xbf3e3f043ef1bf46,0xbe79bf803f0e3f6d,0x3edbbf4ebdc93f75,
0xbf4e3edb3f0ebf35,0xbf80be793f75bdc9,0x3f04bf3ebe483f6d,0x3f71be16bf463ef1,0xbf7dbeac3f7b8000,0xbf2cbf5c3f623f22,0x3f78bd49bf553ec4,0x3f673f18bf7fbe95,
0x3f73be60bf463f0e,0x3f6a3efcbf80be16,0xbf7e3cc93f62bec4,0xbf51bf273f783eac,0x3f7f3e2fbf753e48,0x3f313f4abf67bf04,0xbf77beb83f7f0000,0xbf09bf653f4e3f2c,
0x3ea13f7abf22bf55,0xbecf3f5f3d49bf7d,0xbdfbbf803ef13f6d,0x3f13bf42be793f71,0xbd973f7cbe95bf7b,0xbf393f1d3edbbf5c,0x3e89bf6f3dc93f80,0x3f58bee6bf183f3e,
0x3ec4bf6d00003f80,0x3f6dbec4bf353f35,0xbec43f6d0000bf80,0xbf6d3ec43f35bf35,0x3ec4bf6d00003f80,0x3f6dbec4bf353f35,0xbec43f6d0000bf80,0xbf6d3ec43f35bf35,
0x3f6d3ec4bf808000,0x3ec43f6dbf35bf35,0xbf6dbec43f808000,0xbec4bf6d3f353f35,0x3f6d3ec4bf808000,0x3ec43f6dbf35bf35,0xbf6dbec43f808000,0xbec4bf6d3f353f35,
0xbf42bf133f753e48,0xbcc9bf7e3edb3f5c,0x3f5f3ecfbf7f0000,0x3e603f73bf18bf3e,0xbee6bf583f463f0e,0x3eb8bf773d493f7d,0x3f1d3f39bf62bec4,0xbe2f3f7fbe79bf71,
0x3f27bf51be953f7b,0x3f80bdfbbf673f04,0xbefc3f6a3dc9bf80,0xbf7a3ea13f4ebf2c,0x3f65bf09bf223f55,0x3f6f3e89bf803e16,0xbf4a3f313ef1bf6d,0xbf7cbd973f78beac,
0xbf7d3eac3f55bf35,0xbf3ebf043f753dc9,0x3f783d49bf7b3ec4,0x3edb3f4ebf46bef1,0xbf183f673e48bf80,0xbf803e793f62bf22,0x3f5cbf2cbf0e3f6d,0x3f713e16bf7f3e95,
0xbe16bf713f0e3f35,0x3f2cbf5cbe953f7f,0xbe793f80be48bf6d,0xbf673f183f22bf62,0xbf4ebedb3f7b8000,0xbd49bf783ef13f46,0x3f043f3ebf55bec4,0xbeac3f7dbdc9bf75,
0xbf513f4a3ef1bf7b,0xbf73bcc93f7dbedb,0x3eb8bf7f3dc93f6d,0x3f77bf09bf3e3f5c,0x3e603f5fbf22bf0e,0xbf273f6a3e79bf80,0xbf39bee63f750000,0x3dfbbf7c3eac3f4e,
0xbf13bf1d3f623e48,0x3ea1bf803e163f67,0x3f6f3d97bf7f3ec4,0x3e893f58bf2cbf04,0xbf7a3efc3f46bf55,0xbf42becf3f78bd49,0x3f31bf65be953f80,0x3f7ebe2fbf713f18,
0x3f46bf62bec43f80,0x3f75bdc9bf7b3f0e,0xbf7f3e953f6dbf35,0xbef1bf223f553e48,0x3f223ef1bf6d0000,0xbe953f7fbe48bf55,0x3dc9bf753ec43f35,0x3f62bf46bf0e3f7b,
0x3f223ef1bf6d8000,0xbe953f7fbe48bf55,0x3dc9bf753ec43f35,0x3f62bf46bf0e3f7b,0xbf463f623ec4bf80,0xbf753dc93f7bbf0e,0x3f7fbe95bf6d3f35,0x3ef13f22bf55be48,
0x3ecfbf7f3dc93f55,0x3f7ebf13bf4e3f67,0x3f093efcbf620000,0xbee63f80bd49bf5c,0x3f313ea1bf753e48,0xbe893f7abe79bf3e,0xbf7c3f1d3f46bf6d,0xbf27beb83f71be16,
0x3f6abd97bf7f3f0e,0x3dfb3f51bf18bedb,0xbf583f5f3ef1bf80,0xbf653cc93f80bf04,0xbf393f733e95bf7b,0xbf773e603f78bf2c,0xbe2fbf4a3f223ec4,0x3f42bf6fbeac3f7d,
0x3eacbf783e483f35,0x3f7dbf2cbf463f75,0xbf803f183f55bf6d,0xbf04bedb3f62bdc9,0xbf673f5c3f0ebf80,0xbf4ebd493f7fbef1,0x3f3e3e16bf7b3ec4,0xbe793f71be95bf22,
0x3f71be79bf7b3f35,0x3e163f3ebf22be95,0xbd49bf4e3f0e3ec4,0x3f5cbf67bef13f7f,0xbedbbf043f558000,0x3f18bf80bdc93f62,0xbf2c3f7d3e48bf6d,0xbf783eac3f75bf46,
0x3f1dbf80bdc93f55,0x3f7abee6bf713f5c,0x3f273e2fbf753ec4,0xbecf3f77be16bf2c,0xbf5f3f6f3ef1bf7b,0xbf513d973f80bf18,0xbea1bf093f460000,0x3f39bf7ebe793f67,
0x3f4abcc9bf7f3f0e,0xbe603f65beacbf04,0xbf423f7c3e95bf6d,0xbf6a3e893f7dbf3e,0xbefcbeb83f62be48,0x3f13bf7fbd493f4e,0x3f73bf58bf223f80,0x3f313dfbbf783edb,
0x3f7bbf55bf353f80,0x3f0e3e48bf6d3ec4,0xbe48bf0e3f350000,0x3f55bf7bbec43f6d,0xbf7b3f553f35bf80,0xbf0ebe483f6dbec4,0x3e483f0ebf350000,0xbf553f7b3ec4bf6d,
0x3e483f0ebf358000,0xbf553f7b3ec4bf6d,0x3f7bbf55bf353f80,0x3f0e3e48bf6d3ec4,0xbe48bf0e3f358000,0x3f55bf7bbec43f6d,0xbf7b3f553f35bf80,0xbf0ebe483f6dbec4,
0x3f7ebf31bf623f7b,0x3e603ee6bf3e3e16,0x3d973f13bf220000,0xbf6a3f773f04bf71,0xbf5f3eb83f7fbf55,0x3e2fbf423edb3e79,0x3ea1bf583e953ec4,0x3f80bf4abf4e3f80,
0xbdfb3f39bef1be48,0xbf7a3f653f2cbf7d,0xbf7f3f513f46bf80,0xbecfbe893f5cbeac,0x3efcbf6f3dc93f0e,0x3f7cbf27bf673f78,0x3f73bf09bf753f6d,0x3cc93f1dbf18bd49,
0x3f2cbe16bf7b3f35,0xbf043f67bdc9bef1,0x3f71bf78bf0e3f6d,0x3f18bd49bf753f22,0xbf803f4e3f55bf80,0xbe79beac3f46be95,0xbedb3f5cbe48bec4,0xbf7d3f3e3f62bf7f,
0xbf3e3f7d3e48bf35,0xbf5c3edb3f7fbf62,0x3eac3e79bf553ec4,0xbf4e3f803e95bf46,0x3d49bf183f0e8000,0x3f78bf71bf223f75,0xbf673f043f7bbf6d,0x3e16bf2c3ef13dc9,
0xbeb83f42be95be48,0xbf7e3f513f5cbf80,0xbf7a3f773f22bf6d,0xbee6bcc93f67bf18,0xbf393ea13f7fbf55,0x3efcbf583e163eac,0x3e2fbf1d3ef10000,0x3f7fbf6abf3e3f78,
0xbf6f3f273f75bf7b,0x3dfbbf133f04bd49,0xbe60be893f46bec4,0x3f65bf80bedb3f4e,0x3f31bf73bdc93f0e,0x3f5fbf09bf7d3f71,0x3f7cbf4abf623f80,0x3d973ecfbf2c3e79,
0x3f75bf46bf6d3f80,0xbdc93ef1bf0e3e48,0x3f62bf7fbec43f35,0x3f22be95bf7b3f55,0x3e95bf223ec40000,0x3f7fbf62bf553f7b,0xbef13dc93f6dbf35,0x3f46bf75be483f0e,
0xbe953f22bec48000,0xbf7f3f623f55bf7b,0x3ef1bdc9bf6d3f35,0xbf463f753e48bf0e,0x3f75bf46bf6d3f80,0xbdc93ef1bf0e3e48,0x3f62bf7fbec43f35,0x3f22be95bf7b3f55,
0x3e2f3dfbbf463f0e,0xbf733f803f04bf3e,0xbecf3f27be950000,0xbf773f583f67bf7d,0x3f7abf5fbf623f7b,0xbd973eb8bf183eac,0x3f31bee6bf7f3f6d,0xbf1d3f51bd49be79,
0xbf7c3f7e3f22bf55,0xbea13cc93f5cbf2c,0xbf6a3f423f75bf80,0x3e89bf093edbbe16,0xbe603efcbef13e48,0xbf7f3f6f3f4ebf71,0xbf393f653dc9bec4,0xbf4a3f133f80bf78,
0xbf783f803f0ebf35,0xbeac3e163f62bf46,0xbf4e3f673e48bec4,0xbf2c3f043f7fbf75,0xbf5c3f3e3f7bbf80,0x3edbbf183e95bdc9,0xbf7d3f713f55bf6d,0x3d49be793f22bef1,
0xbe793d493f55bf35,0x3f71bf7dbef13f22,0xbf183edb3f7bbf6d,0x3f3ebf5cbdc93e95,0x3f04bf2c3e488000,0x3f67bf4ebf753f7f,0x3e16beac3f0ebec4,0x3f80bf78bf463f62,
0x3d97be2f3f22bf0e,0x3f80bf7ebf3e3f4e,0x3e89beb83ef1bec4,0x3f7abf73bf5c3f67,0x3ee6bf093e95be48,0x3f6abf5fbf713f78,0x3f1dbf313dc90000,0x3f51bf42bf7d3f80,
0x3f7fbf7cbf463f55,0xbcc93dfbbf2c3f18,0x3f77bf6fbf623f6d,0xbe603ea1bf043edb,0x3f65bf58bf753f7b,0xbecf3efcbeac3e79,0x3f4abf39bf7f3f80,0xbf133f27be163d49,
0xbf353f35bf803f80,0x3f35bf3500000000,0xbf353f35bf803f80,0x3f35bf3500000000,0xbf353f35bf803f80,0x3f35bf3500000000,0xbf353f35bf803f80,0x3f35bf3500000000,
0x3f35bf3580008000,0x3f35bf353f80bf80,0x3f35bf3580008000,0x3f35bf353f80bf80,0x3f35bf3580008000,0x3f35bf353f80bf80,0x3f35bf3580008000,0x3f35bf353f80bf80,
0x3f653f58bf62bf55,0x3f6a3f5fbf67bf5c,0x3f4a3f39bf46bf35,0x3f513f42bf4ebf3e,0x3f7f3f7cbf7fbf7b,0x3f803f7ebf80bf7d,0x3f773f6fbf75bf6d,0x3f7a3f73bf78bf71,
0x3ee63f09bef1bf0e,0x3ecf3efcbedbbf04,0x3f1d3f31bf22bf35,0x3f133f27bf18bf2c,0x3d973e2fbdc9be48,0x3cc93dfbbd49be16,0x3e893eb8be95bec4,0x3e603ea1be79beac,
0xbf5cbf3e3f553f35,0xbf67bf4e3f623f46,0xbf7dbf713f7b3f6d,0xbf80bf783f7f3f75,0xbe79bd493e480000,0xbeacbe163e953dc9,0xbf18bedb3f0e3ec4,0xbf2cbf043f223ef1,
0xbf04bf2c3f0e3f35,0xbedbbf183ef13f22,0xbe16beac3e483ec4,0xbd49be793dc93e95,0xbf78bf803f7b3f80,0xbf71bf7d3f753f7f,0xbf4ebf673f553f6d,0xbf3ebf5c3f463f62,
0x3f7a3f5fbf75bf55,0x3f7f3f6fbf7dbf67,0x3f313ee6bf22bec4,0x3f4a3f13bf3ebf04,0x3e2fbdfbbdc93e48,0x3ea13cc9be793d49,0xbecfbf273ef13f35,0xbe89bf093eac3f18,
0x3e603efcbe95bf0e,0x3d973eb8be16bedb,0x3f393f65bf46bf6d,0x3f1d3f51bf2cbf5c,0x3f7c3f7ebf7fbf7b,0x3f733f80bf78bf80,0x3f6a3f42bf62bf35,0x3f773f58bf71bf4e,
0x3f623f7fbf6dbf80,0x3f463f75bf55bf7b,0x3e953f22bec4bf35,0x3dc93ef1be48bf0e,0xbef1bdc93ec40000,0xbf22be953f0e3e48,0xbf75bf463f6d3f35,0xbf7fbf623f7b3f55,
0xbef1bdc93ec48000,0xbf22be953f0e3e48,0xbf75bf463f6d3f35,0xbf7fbf623f7b3f55,0xbf62bf7f3f6d3f80,0xbf46bf753f553f7b,0xbe95bf223ec43f35,0xbdc9bef13e483f0e,
0xbf31bf733f463f7b,0xbefcbf583f183f67,0xbf7cbf4a3f753f35,0xbf7fbf6a3f803f5c,0x3f6f3f27bf62bf0e,0x3f7e3f51bf78bf3e,0x3e60be89bdc93ec4,0x3ee6bcc9beac3e16,
0x3f393ea1bf22be48,0x3f5f3f09bf4ebedb,0xbe2fbf1d3e953f35,0x3d97becf3d493f04,0x3eb83f42bef1bf55,0x3dfb3f13be79bf2c,0x3f7a3f77bf7fbf6d,0x3f653f80bf71bf7d,
0x3d493f18be48bf35,0xbe793eac3dc9bef1,0xbf67bf043f553ec4,0xbf7dbf3e3f753f22,0x3f2c3e16bf0e0000,0x3f5c3edbbf46be95,0x3f713f78bf7bbf6d,0x3f4e3f80bf62bf7f,
0xbf80bf4e3f7b3f35,0xbf78bf713f7f3f62,0xbedbbf5c3f0e3f6d,0xbe16bf2c3e953f46,0x3f3e3f7dbf55bf80,0x3f043f67bf22bf75,0xbeac3e793e48bec4,0xbf18bd493ef1bdc9,
0x3f5f3eb8bf46be48,0x3f7c3f27bf71bf04,0xbea1bf583ef13f6d,0x3cc9bf1d3e163f3e,0xbf7ebf313f753f0e,0xbf7abf653f803f4e,0xbd973f13bdc9bf35,0xbecf3e893e79bedb,
0x3efc3f6fbf22bf7b,0x3e2f3f42beacbf5c,0x3f733f09bf62bec4,0x3f803f4abf7dbf2c,0xbdfbbf393e953f55,0x3e60bee6bd493f18,0xbf7fbf513f7f3f35,0xbf6abf773f783f67,
0xbf0ebf7b3f353f80,0xbe48bf553ec43f6d,0x3f553e48bf350000,0x3f7b3f0ebf6dbec4,0x3f0e3f7bbf35bf80,0x3e483f55bec4bf6d,0xbf55be483f350000,0xbf7bbf0e3f6d3ec4,
0x3f553e48bf358000,0x3f7b3f0ebf6dbec4,0x3f0e3f7bbf35bf80,0x3e483f55bec4bf6d,0xbf55be483f358000,0xbf7bbf0e3f6d3ec4,0xbf0ebf7b3f353f80,0xbe48bf553ec43f6d,
0xbefc3eb83e95bf0e,0xbf51bd973f2cbe16,0x3f733f58bf7fbf35,0x3f393f7ebf5cbf71,0x3f4a3cc9bf223e48,0x3f7a3ee6bf67be79,0xbf42bf7c3f623f6d,0xbecfbf773f183f80,
0xbf5fbf6f3f753f55,0xbf13bf7f3f3e3f7d,0xbea13f093dc9bf35,0xbf313dfb3f04beac,0x3f1d3f80bf46bf7b,0x3e603f65bedbbf78,0x3f27be2fbef13ec4,0x3f6a3e89bf4ebd49,
0x3f673f5cbf7bbf35,0x3f183f80bf46bf75,0xbf3e3e163f0ebec4,0xbf78beac3f623dc9,0xbf71be793f550000,0xbf7dbf2c3f7f3ef1,0x3d49bf4e3e483f6d,0x3f04bedbbe953f22,
0xbedb3f043e48bf35,0xbf4e3d493f22be95,0xbf2cbf7d3f553f6d,0xbe79bf713ef13f7f,0xbeacbf783f0e3f80,0x3e16bf3e3dc93f62,0x3f803f18bf7bbec4,0x3f5c3f67bf75bf46,
0x3f31bea1bef13f0e,0x3f773e60bf5c3d49,0xbf7cbf1d3f7f3ec4,0xbf42bf6f3f673f4e,0x3ecf3f7fbf22bf7b,0xbdfb3f51be16bf71,0x3f09befcbe953f35,0x3f653cc9bf3e3e79,
0x3f393f73bf62bf55,0x3e893f7abf04bf80,0x3e2fbf4a3dc93f6d,0x3f27beb8bedb3f18,0xbf6abd973f46be48,0xbf7ebf133f7d3eac,0x3f583f5fbf75bf35,0x3ee63f80bf2cbf78,
0x3dc93f75bec4bf80,0xbef13f223e48bf55,0xbf46bf623f6d3f35,0xbe95bf7f3f0e3f7b,0x3f7f3e95bf6d0000,0x3f623f46bf7bbf0e,0xbf223ef13ec4bf35,0xbf75bdc93f55be48,
0xbf7fbe953f6d8000,0xbf62bf463f7b3f0e,0x3f22bef1bec43f35,0x3f753dc9bf553e48,0x3dc93f75bec4bf80,0xbef13f223e48bf55,0xbf46bf623f6d3f35,0xbe95bf7f3f0e3f7b,
0x3f7a3efcbf7fbe48,0x3f273f6abf5cbf3e,0xbf31bf653f623f35,0xbdfbbf7c3edb3f7d,0x3f13bf1dbe953f55,0x3f73bcc9bf4e3eac,0xbf6f3d973f46bec4,0xbf77bf093f803e79,
0xbe603f5fbdc9bf7b,0xbf423ecf3f04bf2c,0x3f39bee6bef13f35,0x3f7e3e2fbf673e16,0x3f513f4abf75bf0e,0x3ea13f80bf18bf71,0xbeb8bf7f3f223f6d,0x3e89bf583d493f78,
0x3f4ebedbbf0e3f35,0x3f803e79bf753dc9,0xbf043f3e3e48bf6d,0xbf713e163f46bef1,0x3f7d3eacbf7b0000,0x3f2c3f5cbf62bf22,0xbf783d493f55bec4,0xbf67bf183f7f3e95,
0x3f183f67bf55bf35,0xbd493f78be95bf7f,0xbf5cbf2c3f7b3ec4,0xbeacbf7d3f223f62,0xbe163f71be48bf80,0xbf3e3f043ef1bf46,0xbe79bf803f0e3f6d,0x3edbbf4ebdc93f75,
0x3ee6bf58bdc93f7b,0x3f6fbe89bf3e3f18,0xbf1d3f393e95bf6d,0xbf7c3d973f5cbedb,0x3f42bf13bef13f55,0x3f803dfbbf713e79,0xbf5f3ecf3f22bf35,0xbf7abea13f7dbd49,
0x3f653f09bf7fbe48,0x3eb83f77bf2cbf4e,0xbf4abf313f753ec4,0xbe2fbf7f3f043f67,0x3f273f51bf62bf0e,0xbcc93f7ebeacbf78,0xbefcbf6a3f463f35,0x3e60bf733e163f80,
0x3ec4bf6d00003f80,0x3f6dbec4bf353f35,0xbec43f6d0000bf80,0xbf6d3ec43f35bf35,0x3ec4bf6d00003f80,0x3f6dbec4bf353f35,0xbec43f6d0000bf80,0xbf6d3ec43f35bf35,
0x3f6d3ec4bf808000,0x3ec43f6dbf35bf35,0xbf6dbec43f808000,0xbec4bf6d3f353f35,0x3f6d3ec4bf808000,0x3ec43f6dbf35bf35,0xbf6dbec43f808000,0xbec4bf6d3f353f35,
0xbd97bf7c3ef13f55,0x3f31bf4abeac3f78,0x3e893f6fbf22bf35,0xbf093f653e16bf80,0x3ea1bf7a3dc93f7b,0x3f6abefcbf2c3f4e,0xbdfb3f80be95bf6d,0xbf513f273f04bf67,
0x3f7fbe2fbf623f0e,0x3f393f1dbf71be79,0xbf773eb83f46bf35,0xbf58bee63f7d3d49,0x3f733e60bf7f3e48,0x3ecf3f5fbf3ebf18,0xbf7ebcc93f75bec4,0xbf13bf423f5c3edb,
0xbe16bf713f0e3f35,0x3f2cbf5cbe953f7f,0xbe793f80be48bf6d,0xbf673f183f22bf62,0xbf4ebedb3f7b0000,0xbd49bf783ef13f46,0x3f043f3ebf55bec4,0xbeac3f7dbdc9bf75,
0x3f7dbeacbf553f35,0x3f3e3f04bf75bdc9,0xbf78bd493f7bbec4,0xbedbbf4e3f463ef1,0x3f18bf67be483f80,0x3f80be79bf623f22,0xbf5c3f2c3f0ebf6d,0xbf71be163f7fbe95,
0x3e2fbf7e3e953f55,0x3f65bf31bf183f71,0x3ecf3f42bf46bec4,0xbefc3f7a3d49bf78,0xbf58be893f7fbe48,0xbd97bf6f3f043f2c,0x3f80bea1bf623f35,0x3f1d3f13bf67be16,
0x3f7cbdfbbf753f0e,0x3ee63f39bf4ebeac,0xbf6a3f273f22bf6d,0xbf5fbe603f80be79,0x3f09bf77bdc93f7b,0x3f7fbeb8bf5c3f3e,0x3cc93f73bef1bf35,0xbf4a3f513edbbf7d,
0xbf463f623ec4bf80,0xbf753dc93f7bbf0e,0x3f7fbe95bf6d3f35,0x3ef13f22bf55be48,0xbf22bef13f6d0000,0x3e95bf7f3e483f55,0xbdc93f75bec4bf35,0xbf623f463f0ebf7b,
0xbf22bef13f6d8000,0x3e95bf7f3e483f55,0xbdc93f75bec4bf35,0xbf623f463f0ebf7b,0x3f46bf62bec43f80,0x3f75bdc9bf7b3f0e,0xbf7f3e953f6dbf35,0xbef1bf223f553e48,
0xbf6f3f423f22bf7b,0xbf4abe2f3f7dbeac,0x3e60bf773e953f35,0x3f73bf39bf2c3f78,0x3cc9bf653ef13f0e,0x3f5fbf58bf043f80,0x3f513dfbbf7f3ec4,0xbd973f6abedbbf18,
0xbeb8bf273f463e48,0x3f1dbf7cbe163f71,0x3f7abe89bf753f35,0x3ea13f31bf3ebe79,0x3f80bee6bf623f55,0x3efc3f09bf5cbd49,0xbf133f7e3dc9bf6d,0xbf7f3ecf3f67bf4e,
0xbf713e793f7bbf35,0xbe16bf3e3f223e95,0x3d493f4ebf0ebec4,0xbf5c3f673ef1bf7f,0x3edb3f04bf550000,0xbf183f803dc9bf62,0x3f2cbf7dbe483f6d,0x3f78beacbf753f46,
0x3eacbf783e483f35,0x3f7dbf2cbf463f75,0xbf803f183f55bf6d,0xbf04bedb3f62bdc9,0xbf673f5c3f0ebf80,0xbf4ebd493f7fbef1,0x3f3e3e16bf7b3ec4,0xbe793f71be95bf22,
0xbdfbbf313f223e48,0x3f58bf73bedb3f78,0x3f7fbf13bf623f6d,0x3eb83efcbf4e3d49,0xbe893f6abe95bf0e,0xbf7c3f423f3ebf7d,0xbf653e603f7fbf35,0x3cc9bf4a3f043eac,
0x3f7ebf39bf463f7b,0x3f093ea1bf673e79,0xbd973f51bef1bec4,0xbf6f3f5f3f18bf80,0xbf773ecf3f75bf55,0xbe2fbf273f2c3e16,0x3ee6bf7a3dc93f35,0x3f80bf1dbf5c3f71,
0x3f7bbf55bf353f80,0x3f0e3e48bf6d3ec4,0xbe48bf0e3f350000,0x3f55bf7bbec43f6d,0xbf7b3f553f35bf80,0xbf0ebe483f6dbec4,0x3e483f0ebf350000,0xbf553f7b3ec4bf6d,
0x3e483f0ebf358000,0xbf553f7b3ec4bf6d,0x3f7bbf55bf353f80,0x3f0e3e48bf6d3ec4,0xbe48bf0e3f358000,0x3f55bf7bbec43f6d,0xbf7b3f553f35bf80,0xbf0ebe483f6dbec4,
0x3f1d3cc9bf753f0e,0xbf093f73bd49bf18,0xbf273f7c3dc9bf35,0xbf6f3efc3f78bf67,0xbe89becf3f46be48,0x3f51bf7fbeac3f5c,0x3f65bf7abef13f6d,0x3f39bdfbbf7d3f2c,
0xbf4a3f803e95bf55,0xbf583ea13f80bf4e,0xbf423e2f3f7fbf35,0x3eb8bf5f3e793edb,0x3f77bf6abf223f7b,0x3f133d97bf713f04,0x3ee63e60bf623ec4,0xbf313f7e3e16bf3e,
0xbf3e3f7d3e48bf35,0xbf5c3edb3f7fbf62,0x3eac3e79bf553ec4,0xbf4e3f803e95bf46,0x3d49bf183f0e0000,0x3f78bf71bf223f75,0xbf673f043f7bbf6d,0x3e16bf2c3ef13dc9,
0xbf2c3e163f7bbf35,0x3f04bf673dc93ef1,0xbf713f783f0ebf6d,0xbf183d493f75bf22,0x3f80bf4ebf553f80,0x3e793eacbf463e95,0x3edbbf5c3e483ec4,0x3f7dbf3ebf623f7f,
0xbecfbd973f62bf0e,0x3f4abf7cbe793f2c,0x3f09bf5f3dc93ec4,0x3f73bf31bf713f7d,0x3f80bf65bf463f7b,0x3e893e60bf4e3edb,0x3f13bdfbbf753f35,0xbf273f6f3d49bf04,
0x3f6abf7fbef13f55,0x3f1dbe2fbf783f3e,0x3f58befcbf7f3f6d,0xbea13f39beacbe16,0x3cc93ee6bf223e48,0xbf773f7a3f18bf67,0xbf513f7e3e95bf35,0xbf423eb83f80bf5c,
0xbf753f463f6dbf80,0x3dc9bef13f0ebe48,0xbf623f7f3ec4bf35,0xbf223e953f7bbf55,0xbe953f22bec40000,0xbf7f3f623f55bf7b,0x3ef1bdc9bf6d3f35,0xbf463f753e48bf0e,
0x3e95bf223ec48000,0x3f7fbf62bf553f7b,0xbef13dc93f6dbf35,0x3f46bf75be483f0e,0xbf753f463f6dbf80,0x3dc9bef13f0ebe48,0xbf623f7f3ec4bf35,0xbf223e953f7bbf55,
0x3f13bf4a3dc93e48,0x3f65bf39bf783f80,0x3f6fbf7fbef13f35,0x3efcbe60bf713f4e,0xbf093e893f75bf55,0x3f42bf6abe163edb,0x3cc9bea13f22bec4,0x3f7ebf7cbf2c3f5c,
0x3f51bf1dbf7f3f7b,0xbee63f31be79bd49,0x3eb8bd97bf623f35,0xbf5f3f7a3eacbf18,0x3f58bf77be953f0e,0x3f27becfbf7d3f67,0x3f80bf73bf463f6d,0x3dfb3e2fbf3e3f04,
0x3e79bd49bf553f35,0xbf713f7d3ef1bf22,0x3f18bedbbf7b3f6d,0xbf3e3f5c3dc9be95,0xbf043f2cbe480000,0xbf673f4e3f75bf7f,0xbe163eacbf0e3ec4,0xbf803f783f46bf62,
0xbf783f803f0ebf35,0xbeac3e163f62bf46,0xbf4e3f673e48bec4,0xbf2c3f043f7fbf75,0xbf5c3f3e3f7bbf80,0x3edbbf183e95bdc9,0xbf7d3f713f55bf6d,0x3d49be793f22bef1,
0xbf273f133f7fbf7b,0x3f39bf4abd493e16,0xbefc3ecf3f75bf6d,0x3f58bf65be793eac,0xbea13e603f62bf55,0x3f6fbf77bedb3f04,0xbdfb3cc93f46bf35,0x3f7cbf7fbf183f2c,
0x3f42bf51bdc93e48,0x3f31bf1dbf803f7d,0x3f5fbf6abe953ec4,0x3f09bee6bf783f71,0x3f73bf7abef13f0e,0x3eb8be89bf673f5c,0x3f7ebf80bf223f35,0x3e2fbd97bf4e3f3e,
0xbf353f35bf803f80,0x3f35bf3500000000,0xbf353f35bf803f80,0x3f35bf3500000000,0xbf353f35bf803f80,0x3f35bf3500000000,0xbf353f35bf803f80,0x3f35bf3500000000,
0x3f35bf3580008000,0x3f35bf353f80bf80,0x3f35bf3580008000,0x3f35bf353f80bf80,0x3f35bf3580008000,0x3f35bf353f80bf80,0x3f35bf3580008000,0x3f35bf353f80bf80,
0x3f733f7abf75bf7b,0x3f6f3f77bf71bf78,0x3f7e3f80bf7fbf80,0x3f7c3f7fbf7dbf80,0x3f423f51bf46bf55,0x3f393f4abf3ebf4e,0x3f5f3f6abf62bf6d,0x3f583f65bf5cbf67,
0xbea1be603e953e48,0xbeb8be893eac3e79,0xbdfbbcc93dc98000,0xbe2fbd973e163d49,0xbf27bf133f223f0e,0xbf31bf1d3f2c3f18,0xbefcbecf3ef13ec4,0xbf09bee63f043edb,
0xbf04bf2c3f0e3f35,0xbedbbf183ef13f22,0xbe16beac3e483ec4,0xbd49be793dc93e95,0xbf78bf803f7b3f80,0xbf71bf7d3f753f7f,0xbf4ebf673f553f6d,0xbf3ebf5c3f463f62,
0x3f5c3f3ebf55bf35,0x3f673f4ebf62bf46,0x3f7d3f71bf7bbf6d,0x3f803f78bf7fbf75,0x3e793d49be488000,0x3eac3e16be95bdc9,0x3f183edbbf0ebec4,0x3f2c3f04bf22bef1,
0xbf09be893ef13e48,0xbf27becf3f183eac,0x3cc93ea1bdc9bec4,0xbdfb3e2f3d49be79,0x3f133f4abf22bf55,0x3ee63f31bf04bf3e,0x3f6f3f7fbf75bf80,0x3f5f3f7abf67bf7d,
0xbf58bf773f623f7b,0xbf42bf6a3f4e3f71,0xbf80bf733f7f3f6d,0xbf7ebf7c3f803f78,0xbf51bf1d3f463f0e,0xbf65bf393f5c3f2c,0xbeb8bd973e958000,0xbefcbe603edb3e16,
0xbf62bf7f3f6d3f80,0xbf46bf753f553f7b,0xbe95bf223ec43f35,0xbdc9bef13e483f0e,0x3ef13dc9bec40000,0x3f223e95bf0ebe48,0x3f753f46bf6dbf35,0x3f7f3f62bf7bbf55,
0x3ef13dc9bec48000,0x3f223e95bf0ebe48,0x3f753f46bf6dbf35,0x3f7f3f62bf7bbf55,0x3f623f7fbf6dbf80,0x3f463f75bf55bf7b,0x3e953f22bec4bf35,0x3dc93ef1be48bf0e,
0xbcc93ee6bdc9bf0e,0xbe893e603e16beac,0x3f513f7ebf62bf80,0x3f273f6fbf3ebf78,0xbf6abf7f3f753f7b,0xbf4abf7c3f5c3f80,0xbf58befc3f463ec4,0xbf73bf313f673f18,
0xbf80bf653f7f3f55,0xbf77bf7a3f7d3f71,0xbf13bdfb3ef18000,0xbf42beb83f2c3e79,0x3ecfbd97be953e48,0x3f1d3e2fbf04bd49,0xbf09bf5f3f223f6d,0xbea1bf393edb3f4e,
0x3f803f4ebf7bbf35,0x3f783f71bf7fbf62,0x3edb3f5cbf0ebf6d,0x3e163f2cbe95bf46,0xbf3ebf7d3f553f80,0xbf04bf673f223f75,0x3eacbe79be483ec4,0x3f183d49bef13dc9,
0x3d493f18be48bf35,0xbe793eac3dc9bef1,0xbf67bf043f553ec4,0xbf7dbf3e3f753f22,0x3f2c3e16bf0e8000,0x3f5c3edbbf46be95,0x3f713f78bf7bbf6d,0x3f4e3f80bf62bf7f,
0x3e89becfbdc93f0e,0x3f13bd97bedb3e79,0xbf65bf7a3f753f6d,0xbf31bf7e3f4e3f80,0xbf1d3cc93ef1be48,0xbf58bea13f3e3e16,0x3f273f7cbf46bf80,0x3eb83f5fbf04bf71,
0x3f773f6abf7fbf55,0x3f513f7fbf67bf78,0x3ee6be60be953ec4,0x3f393dfbbf183d49,0xbf4abf803f623f7b,0xbf09bf733f2c3f7d,0xbf42be2f3f228000,0xbf6fbefc3f5c3eac,
0xbf0ebf7b3f353f80,0xbe48bf553ec43f6d,0x3f553e48bf350000,0x3f7b3f0ebf6dbec4,0x3f0e3f7bbf35bf80,0x3e483f55bec4bf6d,0xbf55be483f350000,0xbf7bbf0e3f6d3ec4,
0x3f553e48bf358000,0x3f7b3f0ebf6dbec4,0x3f0e3f7bbf35bf80,0x3e483f55bec4bf6d,0xbf55be483f358000,0xbf7bbf0e3f6d3ec4,0xbf0ebf7b3f353f80,0xbe48bf553ec43f6d,
0xbf77becf3f623e48,0xbf7cbf423f803f18,0x3ee63f7abf22bf80,0x3cc93f4abe79bf67,0x3f7e3f39bf7fbf0e,0x3f583f73bf71bf5c,0xbd97bf513e953f6d,0x3eb8befcbe163f2c,
0xbe89bf6a3ef13f7b,0x3e2fbf273d493f4e,0xbf65be603f468000,0xbf80bf1d3f783edb,0xbdfb3f31bdc9bf55,0xbf093ea13eacbf04,0x3f7f3f13bf75bec4,0x3f6f3f5fbf7dbf3e,
0xbedb3f043e48bf35,0xbf4e3d493f22be95,0xbf2cbf7d3f553f6d,0xbe79bf713ef13f7f,0xbeacbf783f0e3f80,0x3e16bf3e3dc93f62,0x3f803f18bf7bbec4,0x3f5c3f67bf75bf46,
0xbf67bf5c3f7b3f35,0xbf18bf803f463f75,0x3f3ebe16bf0e3ec4,0x3f783eacbf62bdc9,0x3f713e79bf558000,0x3f7d3f2cbf7fbef1,0xbd493f4ebe48bf6d,0xbf043edb3e95bf22,
0x3cc93f65be95bf7b,0xbefc3f093e79bf3e,0x3f51bdfbbf223ec4,0x3f7f3ecfbf71be16,0xbf6fbf423f7f3f0e,0xbf1dbf7c3f4e3f67,0x3e603f77bef1bf80,0xbea13f313d49bf5c,
0xbf80bee63f753e48,0xbf5fbf583f783f2c,0x3f133f7ebf46bf6d,0x3d973f6abeacbf7d,0x3eb8bf27bdc93f55,0x3f4abe2fbf183edb,0xbf7abe893f628000,0xbf73bf393f803f04,
0xbdc9bf753ec43f80,0x3ef1bf22be483f55,0x3f463f62bf6dbf35,0x3e953f7fbf0ebf7b,0xbf7fbe953f6d0000,0xbf62bf463f7b3f0e,0x3f22bef1bec43f35,0x3f753dc9bf553e48,
0x3f7f3e95bf6d8000,0x3f623f46bf7bbf0e,0xbf223ef13ec4bf35,0xbf75bdc93f55be48,0xbdc9bf753ec43f80,0x3ef1bf22be483f55,0x3f463f62bf6dbf35,0x3e953f7fbf0ebf7b,
0xbf09bf773f463f55,0x3d97bf6f3e793f80,0xbcc93f73be95bf80,0xbf1d3f133eacbf4e,0xbf7cbdfb3f62be48,0xbf65bf313f7d3edb,0x3f6a3f27bf7fbec4,0x3efc3f7abf3ebf5c,
0x3f58be89bf223f0e,0x3f7f3eb8bf78bd49,0xbf80bea13f758000,0xbf4abf513f713f18,0xbe2fbf7e3ef13f7b,0x3ee6bf39be163f67,0xbecf3f423dc9bf6d,0xbf5f3e603f2cbf04,
0xbf18bf673f553f35,0x3d49bf783e953f7f,0x3f5c3f2cbf7bbec4,0x3eac3f7dbf22bf62,0x3e16bf713e483f80,0x3f3ebf04bef13f46,0x3e793f80bf0ebf6d,0xbedb3f4e3dc9bf75,
0x3f4ebedbbf0e3f35,0x3f803e79bf753dc9,0xbf043f3e3e48bf6d,0xbf713e163f46bef1,0x3f7d3eacbf7b8000,0x3f2c3f5cbf62bf22,0xbf783d493f55bec4,0xbf67bf183f7f3e95,
0xbea1bf7a3f223f55,0x3ecfbf5fbd493f7d,0x3dfb3f80bef1bf6d,0xbf133f423e79bf71,0x3d97bf7c3e953f7b,0x3f39bf1dbedb3f5c,0xbe893f6fbdc9bf80,0xbf583ee63f18bf3e,
0x3f73be60bf463f0e,0x3f6a3efcbf80be16,0xbf7e3cc93f62bec4,0xbf51bf273f783eac,0x3f7f3e2fbf753e48,0x3f313f4abf67bf04,0xbf77beb83f7f8000,0xbf09bf653f4e3f2c,
0x3ec4bf6d00003f80,0x3f6dbec4bf353f35,0xbec43f6d0000bf80,0xbf6d3ec43f35bf35,0x3ec4bf6d00003f80,0x3f6dbec4bf353f35,0xbec43f6d0000bf80,0xbf6d3ec43f35bf35,
0x3f6d3ec4bf808000,0x3ec43f6dbf35bf35,0xbf6dbec43f808000,0xbec4bf6d3f353f35,0x3f6d3ec4bf808000,0x3ec43f6dbf35bf35,0xbf6dbec43f808000,0xbec4bf6d3f353f35,
0x3f27bf51be953f7b,0x3f80bdfbbf673f04,0xbefc3f6a3dc9bf80,0xbf7a3ea13f4ebf2c,0x3f65bf09bf223f55,0x3f6f3e89bf803e16,0xbf4a3f313ef1bf6d,0xbf7cbd973f78beac,
0x3f423f13bf75be48,0x3cc93f7ebedbbf5c,0xbf5fbecf3f7f8000,0xbe60bf733f183f3e,0x3ee63f58bf46bf0e,0xbeb83f77bd49bf7d,0xbf1dbf393f623ec4,0x3e2fbf7f3e793f71,
0x3f7dbeacbf553f35,0x3f3e3f04bf75bdc9,0xbf78bd493f7bbec4,0xbedbbf4e3f463ef1,0x3f18bf67be483f80,0x3f80be79bf623f22,0xbf5c3f2c3f0ebf6d,0xbf71be163f7fbe95,
0x3e163f71bf0ebf35,0xbf2c3f5c3e95bf7f,0x3e79bf803e483f6d,0x3f67bf18bf223f62,0x3f4e3edbbf7b8000,0x3d493f78bef1bf46,0xbf04bf3e3f553ec4,0x3eacbf7d3dc93f75,
0x3f133f1dbf62be48,0xbea13f80be16bf67,0xbf6fbd973f7fbec4,0xbe89bf583f2c3f04,0x3f7abefcbf463f55,0x3f423ecfbf783d49,0xbf313f653e95bf80,0xbf7e3e2f3f71bf18,
0xbf513f4a3ef1bf7b,0xbf73bcc93f7dbedb,0x3eb8bf7f3dc93f6d,0x3f77bf09bf3e3f5c,0x3e603f5fbf22bf0e,0xbf273f6a3e79bf80,0xbf39bee63f758000,0x3dfbbf7c3eac3f4e,
0x3f46bf62bec43f80,0x3f75bdc9bf7b3f0e,0xbf7f3e953f6dbf35,0xbef1bf223f553e48,0x3f223ef1bf6d0000,0xbe953f7fbe48bf55,0x3dc9bf753ec43f35,0x3f62bf46bf0e3f7b,
0x3f223ef1bf6d8000,0xbe953f7fbe48bf55,0x3dc9bf753ec43f35,0x3f62bf46bf0e3f7b,0xbf463f623ec4bf80,0xbf753dc93f7bbf0e,0x3f7fbe95bf6d3f35,0x3ef13f22bf55be48,
0x3f6abd97bf7f3f0e,0x3dfb3f51bf18bedb,0xbf583f5f3ef1bf80,0xbf653cc93f80bf04,0xbf393f733e95bf7b,0xbf773e603f78bf2c,0xbe2fbf4a3f223ec4,0x3f42bf6fbeac3f7d,
0xbecf3f7fbdc9bf55,0xbf7e3f133f4ebf67,0xbf09befc3f628000,0x3ee6bf803d493f5c,0xbf31bea13f75be48,0x3e89bf7a3e793f3e,0x3f7cbf1dbf463f6d,0x3f273eb8bf713e16,
0xbeac3f78be48bf35,0xbf7d3f2c3f46bf75,0x3f80bf18bf553f6d,0x3f043edbbf623dc9,0x3f67bf5cbf0e3f80,0x3f4e3d49bf7f3ef1,0xbf3ebe163f7bbec4,0x3e79bf713e953f22,
0xbf713e793f7bbf35,0xbe16bf3e3f223e95,0x3d493f4ebf0ebec4,0xbf5c3f673ef1bf7f,0x3edb3f04bf558000,0xbf183f803dc9bf62,0x3f2cbf7dbe483f6d,0x3f78beacbf753f46,
0xbf4a3cc93f7fbf0e,0x3e60bf653eac3f04,0x3f42bf7cbe953f6d,0x3f6abe89bf7d3f3e,0x3efc3eb8bf623e48,0xbf133f7f3d49bf4e,0xbf733f583f22bf80,0xbf31bdfb3f78bedb,
0x3f1dbf80bdc93f55,0x3f7abee6bf713f5c,0x3f273e2fbf753ec4,0xbecf3f77be16bf2c,0xbf5f3f6f3ef1bf7b,0xbf513d973f80bf18,0xbea1bf093f468000,0x3f39bf7ebe793f67,
0x3f7bbf55bf353f80,0x3f0e3e48bf6d3ec4,0xbe48bf0e3f350000,0x3f55bf7bbec43f6d,0xbf7b3f553f35bf80,0xbf0ebe483f6dbec4,0x3e483f0ebf350000,0xbf553f7b3ec4bf6d,
0x3e483f0ebf358000,0xbf553f7b3ec4bf6d,0x3f7bbf55bf353f80,0x3f0e3e48bf6d3ec4,0xbe48bf0e3f358000,0x3f55bf7bbec43f6d,0xbf7b3f553f35bf80,0xbf0ebe483f6dbec4,
0xbdfb3f39bef1be48,0xbf7a3f653f2cbf7d,0xbf7f3f513f46bf80,0xbecfbe893f5cbeac,0x3efcbf6f3dc93f0e,0x3f7cbf27bf673f78,0x3f73bf09bf753f6d,0x3cc93f1dbf18bd49,
0xbf7e3f313f62bf7b,0xbe60bee63f3ebe16,0xbd97bf133f228000,0x3f6abf77bf043f71,0x3f5fbeb8bf7f3f55,0xbe2f3f42bedbbe79,0xbea13f58be95bec4,0xbf803f4a3f4ebf80,
0xbf2c3e163f7bbf35,0x3f04bf673dc93ef1,0xbf713f783f0ebf6d,0xbf183d493f75bf22,0x3f80bf4ebf553f80,0x3e793eacbf463e95,0x3edbbf5c3e483ec4,0x3f7dbf3ebf623f7f,
0x3f3ebf7dbe483f35,0x3f5cbedbbf7f3f62,0xbeacbe793f55bec4,0x3f4ebf80be953f46,0xbd493f18bf0e8000,0xbf783f713f22bf75,0x3f67bf04bf7b3f6d,0xbe163f2cbef1bdc9,
0x3f6fbf27bf753f7b,0xbdfb3f13bf043d49,0x3e603e89bf463ec4,0xbf653f803edbbf4e,0xbf313f733dc9bf0e,0xbf5f3f093f7dbf71,0xbf7c3f4a3f62bf80,0xbd97becf3f2cbe79,
0xbeb83f42be95be48,0xbf7e3f513f5cbf80,0xbf7a3f773f22bf6d,0xbee6bcc93f67bf18,0xbf393ea13f7fbf55,0x3efcbf583e163eac,0x3e2fbf1d3ef18000,0x3f7fbf6abf3e3f78,
0x3f75bf46bf6d3f80,0xbdc93ef1bf0e3e48,0x3f62bf7fbec43f35,0x3f22be95bf7b3f55,0x3e95bf223ec40000,0x3f7fbf62bf553f7b,0xbef13dc93f6dbf35,0x3f46bf75be483f0e,
0xbe953f22bec48000,0xbf7f3f623f55bf7b,0x3ef1bdc9bf6d3f35,0xbf463f753e48bf0e,0x3f75bf46bf6d3f80,0xbdc93ef1bf0e3e48,0x3f62bf7fbec43f35,0x3f22be95bf7b3f55,
0xbf7c3f7e3f22bf55,0xbea13cc93f5cbf2c,0xbf6a3f423f75bf80,0x3e89bf093edbbe16,0xbe603efcbef13e48,0xbf7f3f6f3f4ebf71,0xbf393f653dc9bec4,0xbf4a3f133f80bf78,
0xbe2fbdfb3f46bf0e,0x3f73bf80bf043f3e,0x3ecfbf273e958000,0x3f77bf58bf673f7d,0xbf7a3f5f3f62bf7b,0x3d97beb83f18beac,0xbf313ee63f7fbf6d,0x3f1dbf513d493e79,
0x3f78bf80bf0e3f35,0x3eacbe16bf623f46,0x3f4ebf67be483ec4,0x3f2cbf04bf7f3f75,0x3f5cbf3ebf7b3f80,0xbedb3f18be953dc9,0x3f7dbf71bf553f6d,0xbd493e79bf223ef1,
0x3e79bd49bf553f35,0xbf713f7d3ef1bf22,0x3f18bedbbf7b3f6d,0xbf3e3f5c3dc9be95,0xbf043f2cbe488000,0xbf673f4e3f75bf7f,0xbe163eacbf0e3ec4,0xbf803f783f46bf62,
0xbf7f3f7c3f46bf55,0x3cc9bdfb3f2cbf18,0xbf773f6f3f62bf6d,0x3e60bea13f04bedb,0xbf653f583f75bf7b,0x3ecfbefc3eacbe79,0xbf4a3f393f7fbf80,0x3f13bf273e16bd49,
0x3d97be2f3f22bf0e,0x3f80bf7ebf3e3f4e,0x3e89beb83ef1bec4,0x3f7abf73bf5c3f67,0x3ee6bf093e95be48,0x3f6abf5fbf713f78,0x3f1dbf313dc98000,0x3f51bf42bf7d3f80,
0xbf353f35bf803f80,0x3f35bf3500000000,0xbf353f35bf803f80,0x3f35bf3500000000,0xbf353f35bf803f80,0x3f35bf3500000000,0xbf353f35bf803f80,0x3f35bf3500000000,
0x3f35bf3580008000,0x3f35bf353f80bf80,0x3f35bf3580008000,0x3f35bf353f80bf80,0x3f35bf3580008000,0x3f35bf353f80bf80,0x3f35bf3580008000,0x3f35bf353f80bf80,
0x3ee63f09bef1bf0e,0x3ecf3efcbedbbf04,0x3f1d3f31bf22bf35,0x3f133f27bf18bf2c,0x3d973e2fbdc9be48,0x3cc93dfbbd49be16,0x3e893eb8be95bec4,0x3e603ea1be79beac,
0xbf65bf583f623f55,0xbf6abf5f3f673f5c,0xbf4abf393f463f35,0xbf51bf423f4e3f3e,0xbf7fbf7c3f7f3f7b,0xbf80bf7e3f803f7d,0xbf77bf6f3f753f6d,0xbf7abf733f783f71,
0x3f5c3f3ebf55bf35,0x3f673f4ebf62bf46,0x3f7d3f71bf7bbf6d,0x3f803f78bf7fbf75,0x3e793d49be480000,0x3eac3e16be95bdc9,0x3f183edbbf0ebec4,0x3f2c3f04bf22bef1,
0x3f043f2cbf0ebf35,0x3edb3f18bef1bf22,0x3e163eacbe48bec4,0x3d493e79bdc9be95,0x3f783f80bf7bbf80,0x3f713f7dbf75bf7f,0x3f4e3f67bf55bf6d,0x3f3e3f5cbf46bf62,
0xbe60befc3e953f0e,0xbd97beb83e163edb,0xbf39bf653f463f6d,0xbf1dbf513f2c3f5c,0xbf7cbf7e3f7f3f7b,0xbf73bf803f783f80,0xbf6abf423f623f35,0xbf77bf583f713f4e,
0x3f7a3f5fbf75bf55,0x3f7f3f6fbf7dbf67,0x3f313ee6bf22bec4,0x3f4a3f13bf3ebf04,0x3e2fbdfbbdc93e48,0x3ea13cc9be793d49,0xbecfbf273ef13f35,0xbe89bf093eac3f18,
0x3f623f7fbf6dbf80,0x3f463f75bf55bf7b,0x3e953f22bec4bf35,0x3dc93ef1be48bf0e,0xbef1bdc93ec40000,0xbf22be953f0e3e48,0xbf75bf463f6d3f35,0xbf7fbf623f7b3f55,
0xbef1bdc93ec48000,0xbf22be953f0e3e48,0xbf75bf463f6d3f35,0xbf7fbf623f7b3f55,0xbf62bf7f3f6d3f80,0xbf46bf753f553f7b,0xbe95bf223ec43f35,0xbdc9bef13e483f0e,
0x3f393ea1bf22be48,0x3f5f3f09bf4ebedb,0xbe2fbf1d3e953f35,0x3d97becf3d493f04,0x3eb83f42bef1bf55,0x3dfb3f13be79bf2c,0x3f7a3f77bf7fbf6d,0x3f653f80bf71bf7d,
0x3f313f73bf46bf7b,0x3efc3f58bf18bf67,0x3f7c3f4abf75bf35,0x3f7f3f6abf80bf5c,0xbf6fbf273f623f0e,0xbf7ebf513f783f3e,0xbe603e893dc9bec4,0xbee63cc93eacbe16,
0xbd49bf183e483f35,0x3e79beacbdc93ef1,0x3f673f04bf55bec4,0x3f7d3f3ebf75bf22,0xbf2cbe163f0e0000,0xbf5cbedb3f463e95,0xbf71bf783f7b3f6d,0xbf4ebf803f623f7f,
0x3f803f4ebf7bbf35,0x3f783f71bf7fbf62,0x3edb3f5cbf0ebf6d,0x3e163f2cbe95bf46,0xbf3ebf7d3f553f80,0xbf04bf673f223f75,0x3eacbe79be483ec4,0x3f183d49bef13dc9,
0xbefcbf6f3f223f7b,0xbe2fbf423eac3f5c,0xbf73bf093f623ec4,0xbf80bf4a3f7d3f2c,0x3dfb3f39be95bf55,0xbe603ee63d49bf18,0x3f7f3f51bf7fbf35,0x3f6a3f77bf78bf67,
0x3f5f3eb8bf46be48,0x3f7c3f27bf71bf04,0xbea1bf583ef13f6d,0x3cc9bf1d3e163f3e,0xbf7ebf313f753f0e,0xbf7abf653f803f4e,0xbd973f13bdc9bf35,0xbecf3e893e79bedb,
0xbf0ebf7b3f353f80,0xbe48bf553ec43f6d,0x3f553e48bf350000,0x3f7b3f0ebf6dbec4,0x3f0e3f7bbf35bf80,0x3e483f55bec4bf6d,0xbf55be483f350000,0xbf7bbf0e3f6d3ec4,
0x3f553e48bf358000,0x3f7b3f0ebf6dbec4,0x3f0e3f7bbf35bf80,0x3e483f55bec4bf6d,0xbf55be483f358000,0xbf7bbf0e3f6d3ec4,0xbf0ebf7b3f353f80,0xbe48bf553ec43f6d,
0xbf5fbf6f3f753f55,0xbf13bf7f3f3e3f7d,0xbea13f093dc9bf35,0xbf313dfb3f04beac,0x3f1d3f80bf46bf7b,0x3e603f65bedbbf78,0x3f27be2fbef13ec4,0x3f6a3e89bf4ebd49,
0x3efcbeb8be953f0e,0x3f513d97bf2c3e16,0xbf73bf583f7f3f35,0xbf39bf7e3f5c3f71,0xbf4abcc93f22be48,0xbf7abee63f673e79,0x3f423f7cbf62bf6d,0x3ecf3f77bf18bf80,
0xbf67bf5c3f7b3f35,0xbf18bf803f463f75,0x3f3ebe16bf0e3ec4,0x3f783eacbf62bdc9,0x3f713e79bf550000,0x3f7d3f2cbf7fbef1,0xbd493f4ebe48bf6d,0xbf043edb3e95bf22,
0x3edbbf04be483f35,0x3f4ebd49bf223e95,0x3f2c3f7dbf55bf6d,0x3e793f71bef1bf7f,0x3eac3f78bf0ebf80,0xbe163f3ebdc9bf62,0xbf80bf183f7b3ec4,0xbf5cbf673f753f46,
0xbf39bf733f623f55,0xbe89bf7a3f043f80,0xbe2f3f4abdc9bf6d,0xbf273eb83edbbf18,0x3f6a3d97bf463e48,0x3f7e3f13bf7dbeac,0xbf58bf5f3f753f35,0xbee6bf803f2c3f78,
0x3f31bea1bef13f0e,0x3f773e60bf5c3d49,0xbf7cbf1d3f7f3ec4,0xbf42bf6f3f673f4e,0x3ecf3f7fbf22bf7b,0xbdfb3f51be16bf71,0x3f09befcbe953f35,0x3f653cc9bf3e3e79,
0x3dc93f75bec4bf80,0xbef13f223e48bf55,0xbf46bf623f6d3f35,0xbe95bf7f3f0e3f7b,0x3f7f3e95bf6d0000,0x3f623f46bf7bbf0e,0xbf223ef13ec4bf35,0xbf75bdc93f55be48,
0xbf7fbe953f6d8000,0xbf62bf463f7b3f0e,0x3f22bef1bec43f35,0x3f753dc9bf553e48,0x3dc93f75bec4bf80,0xbef13f223e48bf55,0xbf46bf623f6d3f35,0xbe95bf7f3f0e3f7b,
0xbe603f5fbdc9bf7b,0xbf423ecf3f04bf2c,0x3f39bee6bef13f35,0x3f7e3e2fbf673e16,0x3f513f4abf75bf0e,0x3ea13f80bf18bf71,0xbeb8bf7f3f223f6d,0x3e89bf583d493f78,
0xbf7abefc3f7f3e48,0xbf27bf6a3f5c3f3e,0x3f313f65bf62bf35,0x3dfb3f7cbedbbf7d,0xbf133f1d3e95bf55,0xbf733cc93f4ebeac,0x3f6fbd97bf463ec4,0x3f773f09bf80be79,
0xbf4e3edb3f0ebf35,0xbf80be793f75bdc9,0x3f04bf3ebe483f6d,0x3f71be16bf463ef1,0xbf7dbeac3f7b0000,0xbf2cbf5c3f623f22,0x3f78bd49bf553ec4,0x3f673f18bf7fbe95,
0xbf18bf673f553f35,0x3d49bf783e953f7f,0x3f5c3f2cbf7bbec4,0x3eac3f7dbf22bf62,0x3e16bf713e483f80,0x3f3ebf04bef13f46,0x3e793f80bf0ebf6d,0xbedb3f4e3dc9bf75,
0xbf65bf093f7f3e48,0xbeb8bf773f2c3f4e,0x3f4a3f31bf75bec4,0x3e2f3f7fbf04bf67,0xbf27bf513f623f0e,0x3cc9bf7e3eac3f78,0x3efc3f6abf46bf35,0xbe603f73be16bf80,
0x3ee6bf58bdc93f7b,0x3f6fbe89bf3e3f18,0xbf1d3f393e95bf6d,0xbf7c3d973f5cbedb,0x3f42bf13bef13f55,0x3f803dfbbf713e79,0xbf5f3ecf3f22bf35,0xbf7abea13f7dbd49,
0x3ec4bf6d00003f80,0x3f6dbec4bf353f35,0xbec43f6d0000bf80,0xbf6d3ec43f35bf35,0x3ec4bf6d00003f80,0x3f6dbec4bf353f35,0xbec43f6d0000bf80,0xbf6d3ec43f35bf35,
0x3f6d3ec4bf808000,0x3ec43f6dbf35bf35,0xbf6dbec43f808000,0xbec4bf6d3f353f35,0x3f6d3ec4bf808000,0x3ec43f6dbf35bf35,0xbf6dbec43f808000,0xbec4bf6d3f353f35,
0x3f7fbe2fbf623f0e,0x3f393f1dbf71be79,0xbf773eb83f46bf35,0xbf58bee63f7d3d49,0x3f733e60bf7f3e48,0x3ecf3f5fbf3ebf18,0xbf7ebcc93f75bec4,0xbf13bf423f5c3edb,
0x3d973f7cbef1bf55,0xbf313f4a3eacbf78,0xbe89bf6f3f223f35,0x3f09bf65be163f80,0xbea13f7abdc9bf7b,0xbf6a3efc3f2cbf4e,0x3dfbbf803e953f6d,0x3f51bf27bf043f67,
0x3e163f71bf0ebf35,0xbf2c3f5c3e95bf7f,0x3e79bf803e483f6d,0x3f67bf18bf223f62,0x3f4e3edbbf7b0000,0x3d493f78bef1bf46,0xbf04bf3e3f553ec4,0x3eacbf7d3dc93f75,
0xbf7d3eac3f55bf35,0xbf3ebf043f753dc9,0x3f783d49bf7b3ec4,0x3edb3f4ebf46bef1,0xbf183f673e48bf80,0xbf803e793f62bf22,0x3f5cbf2cbf0e3f6d,0x3f713e16bf7f3e95,
0xbf7c3dfb3f75bf0e,0xbee6bf393f4e3eac,0x3f6abf27bf223f6d,0x3f5f3e60bf803e79,0xbf093f773dc9bf7b,0xbf7f3eb83f5cbf3e,0xbcc9bf733ef13f35,0x3f4abf51bedb3f7d,
0x3e2fbf7e3e953f55,0x3f65bf31bf183f71,0x3ecf3f42bf46bec4,0xbefc3f7a3d49bf78,0xbf58be893f7fbe48,0xbd97bf6f3f043f2c,0x3f80bea1bf623f35,0x3f1d3f13bf67be16,
0xbf463f623ec4bf80,0xbf753dc93f7bbf0e,0x3f7fbe95bf6d3f35,0x3ef13f22bf55be48,0xbf22bef13f6d0000,0x3e95bf7f3e483f55,0xbdc93f75bec4bf35,0xbf623f463f0ebf7b,
0xbf22bef13f6d8000,0x3e95bf7f3e483f55,0xbdc93f75bec4bf35,0xbf623f463f0ebf7b,0x3f46bf62bec43f80,0x3f75bdc9bf7b3f0e,0xbf7f3e953f6dbf35,0xbef1bf223f553e48,
0xbeb8bf273f463e48,0x3f1dbf7cbe163f71,0x3f7abe89bf753f35,0x3ea13f31bf3ebe79,0x3f80bee6bf623f55,0x3efc3f09bf5cbd49,0xbf133f7e3dc9bf6d,0xbf7f3ecf3f67bf4e,
0x3f6fbf42bf223f7b,0x3f4a3e2fbf7d3eac,0xbe603f77be95bf35,0xbf733f393f2cbf78,0xbcc93f65bef1bf0e,0xbf5f3f583f04bf80,0xbf51bdfb3f7fbec4,0x3d97bf6a3edb3f18,
0x3f71be79bf7b3f35,0x3e163f3ebf22be95,0xbd49bf4e3f0e3ec4,0x3f5cbf67bef13f7f,0xbedbbf043f550000,0x3f18bf80bdc93f62,0xbf2c3f7d3e48bf6d,0xbf783eac3f75bf46,
0xbeac3f78be48bf35,0xbf7d3f2c3f46bf75,0x3f80bf18bf553f6d,0x3f043edbbf623dc9,0x3f67bf5cbf0e3f80,0x3f4e3d49bf7f3ef1,0xbf3ebe163f7bbec4,0x3e79bf713e953f22,
0xbf7e3f393f46bf7b,0xbf09bea13f67be79,0x3d97bf513ef13ec4,0x3f6fbf5fbf183f80,0x3f77becfbf753f55,0x3e2f3f27bf2cbe16,0xbee63f7abdc9bf35,0xbf803f1d3f5cbf71,
0xbdfbbf313f223e48,0x3f58bf73bedb3f78,0x3f7fbf13bf623f6d,0x3eb83efcbf4e3d49,0xbe893f6abe95bf0e,0xbf7c3f423f3ebf7d,0xbf653e603f7fbf35,0x3cc9bf4a3f043eac,
0x3f7bbf55bf353f80,0x3f0e3e48bf6d3ec4,0xbe48bf0e3f350000,0x3f55bf7bbec43f6d,0xbf7b3f553f35bf80,0xbf0ebe483f6dbec4,0x3e483f0ebf350000,0xbf553f7b3ec4bf6d,
0x3e483f0ebf358000,0xbf553f7b3ec4bf6d,0x3f7bbf55bf353f80,0x3f0e3e48bf6d3ec4,0xbe48bf0e3f358000,0x3f55bf7bbec43f6d,0xbf7b3f553f35bf80,0xbf0ebe483f6dbec4,
0xbf4a3f803e95bf55,0xbf583ea13f80bf4e,0xbf423e2f3f7fbf35,0x3eb8bf5f3e793edb,0x3f77bf6abf223f7b,0x3f133d97bf713f04,0x3ee63e60bf623ec4,0xbf313f7e3e16bf3e,
0xbf1dbcc93f75bf0e,0x3f09bf733d493f18,0x3f27bf7cbdc93f35,0x3f6fbefcbf783f67,0x3e893ecfbf463e48,0xbf513f7f3eacbf5c,0xbf653f7a3ef1bf6d,0xbf393dfb3f7dbf2c,
0x3f3ebf7dbe483f35,0x3f5cbedbbf7f3f62,0xbeacbe793f55bec4,0x3f4ebf80be953f46,0xbd493f18bf0e0000,0xbf783f713f22bf75,0x3f67bf04bf7b3f6d,0xbe163f2cbef1bdc9,
0x3f2cbe16bf7b3f35,0xbf043f67bdc9bef1,0x3f71bf78bf0e3f6d,0x3f18bd49bf753f22,0xbf803f4e3f55bf80,0xbe79beac3f46be95,0xbedb3f5cbe48bec4,0xbf7d3f3e3f62bf7f,
0xbf6a3f7f3ef1bf55,0xbf1d3e2f3f78bf3e,0xbf583efc3f7fbf6d,0x3ea1bf393eac3e16,0xbcc9bee63f22be48,0x3f77bf7abf183f67,0x3f51bf7ebe953f35,0x3f42beb8bf803f5c,
0xbecfbd973f62bf0e,0x3f4abf7cbe793f2c,0x3f09bf5f3dc93ec4,0x3f73bf31bf713f7d,0x3f80bf65bf463f7b,0x3e893e60bf4e3edb,0x3f13bdfbbf753f35,0xbf273f6f3d49bf04,
0xbf753f463f6dbf80,0x3dc9bef13f0ebe48,0xbf623f7f3ec4bf35,0xbf223e953f7bbf55,0xbe953f22bec40000,0xbf7f3f623f55bf7b,0x3ef1bdc9bf6d3f35,0xbf463f753e48bf0e,
0x3e95bf223ec48000,0x3f7fbf62bf553f7b,0xbef13dc93f6dbf35,0x3f46bf75be483f0e,0xbf753f463f6dbf80,0x3dc9bef13f0ebe48,0xbf623f7f3ec4bf35,0xbf223e953f7bbf55,
0x3f51bf1dbf7f3f7b,0xbee63f31be79bd49,0x3eb8bd97bf623f35,0xbf5f3f7a3eacbf18,0x3f58bf77be953f0e,0x3f27becfbf7d3f67,0x3f80bf73bf463f6d,0x3dfb3e2fbf3e3f04,
0xbf133f4abdc9be48,0xbf653f393f78bf80,0xbf6f3f7f3ef1bf35,0xbefc3e603f71bf4e,0x3f09be89bf753f55,0xbf423f6a3e16bedb,0xbcc93ea1bf223ec4,0xbf7e3f7c3f2cbf5c,
0xbe793d493f55bf35,0x3f71bf7dbef13f22,0xbf183edb3f7bbf6d,0x3f3ebf5cbdc93e95,0x3f04bf2c3e480000,0x3f67bf4ebf753f7f,0x3e16beac3f0ebec4,0x3f80bf78bf463f62,
0x3f78bf80bf0e3f35,0x3eacbe16bf623f46,0x3f4ebf67be483ec4,0x3f2cbf04bf7f3f75,0x3f5cbf3ebf7b3f80,0xbedb3f18be953dc9,0x3f7dbf71bf553f6d,0xbd493e79bf223ef1,
0xbf423f513dc9be48,0xbf313f1d3f80bf7d,0xbf5f3f6a3e95bec4,0xbf093ee63f78bf71,0xbf733f7a3ef1bf0e,0xbeb83e893f67bf5c,0xbf7e3f803f22bf35,0xbe2f3d973f4ebf3e,
0xbf273f133f7fbf7b,0x3f39bf4abd493e16,0xbefc3ecf3f75bf6d,0x3f58bf65be793eac,0xbea13e603f62bf55,0x3f6fbf77bedb3f04,0xbdfb3cc93f46bf35,0x3f7cbf7fbf183f2c,
0xbf353f35bf803f80,0x3f35bf3500000000,0xbf353f35bf803f80,0x3f35bf3500000000,0xbf353f35bf803f80,0x3f35bf3500000000,0xbf353f35bf803f80,0x3f35bf3500000000,
0x3f35bf3580008000,0x3f35bf353f80bf80,0x3f35bf3580008000,0x3f35bf353f80bf80,0x3f35bf3580008000,0x3f35bf353f80bf80,0x3f35bf3580008000,0x3f35bf353f80bf80,
0xbea1be603e953e48,0xbeb8be893eac3e79,0xbdfbbcc93dc90000,0xbe2fbd973e163d49,0xbf27bf133f223f0e,0xbf31bf1d3f2c3f18,0xbefcbecf3ef13ec4,0xbf09bee63f043edb,
0xbf73bf7a3f753f7b,0xbf6fbf773f713f78,0xbf7ebf803f7f3f80,0xbf7cbf7f3f7d3f80,0xbf42bf513f463f55,0xbf39bf4a3f3e3f4e,0xbf5fbf6a3f623f6d,0xbf58bf653f5c3f67,
0x3f043f2cbf0ebf35,0x3edb3f18bef1bf22,0x3e163eacbe48bec4,0x3d493e79bdc9be95,0x3f783f80bf7bbf80,0x3f713f7dbf75bf7f,0x3f4e3f67bf55bf6d,0x3f3e3f5cbf46bf62,
0xbf5cbf3e3f553f35,0xbf67bf4e3f623f46,0xbf7dbf713f7b3f6d,0xbf80bf783f7f3f75,0xbe79bd493e488000,0xbeacbe163e953dc9,0xbf18bedb3f0e3ec4,0xbf2cbf043f223ef1,
0x3f583f77bf62bf7b,0x3f423f6abf4ebf71,0x3f803f73bf7fbf6d,0x3f7e3f7cbf80bf78,0x3f513f1dbf46bf0e,0x3f653f39bf5cbf2c,0x3eb83d97be950000,0x3efc3e60bedbbe16,
0xbf09be893ef13e48,0xbf27becf3f183eac,0x3cc93ea1bdc9bec4,0xbdfb3e2f3d49be79,0x3f133f4abf22bf55,0x3ee63f31bf04bf3e,0x3f6f3f7fbf75bf80,0x3f5f3f7abf67bf7d,
0xbf62bf7f3f6d3f80,0xbf46bf753f553f7b,0xbe95bf223ec43f35,0xbdc9bef13e483f0e,0x3ef13dc9bec40000,0x3f223e95bf0ebe48,0x3f753f46bf6dbf35,0x3f7f3f62bf7bbf55,
0x3ef13dc9bec48000,0x3f223e95bf0ebe48,0x3f753f46bf6dbf35,0x3f7f3f62bf7bbf55,0x3f623f7fbf6dbf80,0x3f463f75bf55bf7b,0x3e953f22bec4bf35,0x3dc93ef1be48bf0e,
0xbf80bf653f7f3f55,0xbf77bf7a3f7d3f71,0xbf13bdfb3ef10000,0xbf42beb83f2c3e79,0x3ecfbd97be953e48,0x3f1d3e2fbf04bd49,0xbf09bf5f3f223f6d,0xbea1bf393edb3f4e,
0x3cc9bee63dc93f0e,0x3e89be60be163eac,0xbf51bf7e3f623f80,0xbf27bf6f3f3e3f78,0x3f6a3f7fbf75bf7b,0x3f4a3f7cbf5cbf80,0x3f583efcbf46bec4,0x3f733f31bf67bf18,
0xbf80bf4e3f7b3f35,0xbf78bf713f7f3f62,0xbedbbf5c3f0e3f6d,0xbe16bf2c3e953f46,0x3f3e3f7dbf55bf80,0x3f043f67bf22bf75,0xbeac3e793e48bec4,0xbf18bd493ef1bdc9,
0xbd49bf183e483f35,0x3e79beacbdc93ef1,0x3f673f04bf55bec4,0x3f7d3f3ebf75bf22,0xbf2cbe163f0e8000,0xbf5cbedb3f463e95,0xbf71bf783f7b3f6d,0xbf4ebf803f623f7f,
0xbf77bf6a3f7f3f55,0xbf51bf7f3f673f78,0xbee63e603e95bec4,0xbf39bdfb3f18bd49,0x3f4a3f80bf62bf7b,0x3f093f73bf2cbf7d,0x3f423e2fbf220000,0x3f6f3efcbf5cbeac,
0x3e89becfbdc93f0e,0x3f13bd97bedb3e79,0xbf65bf7a3f753f6d,0xbf31bf7e3f4e3f80,0xbf1d3cc93ef1be48,0xbf58bea13f3e3e16,0x3f273f7cbf46bf80,0x3eb83f5fbf04bf71,
0xbf0ebf7b3f353f80,0xbe48bf553ec43f6d,0x3f553e48bf350000,0x3f7b3f0ebf6dbec4,0x3f0e3f7bbf35bf80,0x3e483f55bec4bf6d,0xbf55be483f350000,0xbf7bbf0e3f6d3ec4,
0x3f553e48bf358000,0x3f7b3f0ebf6dbec4,0x3f0e3f7bbf35bf80,0x3e483f55bec4bf6d,0xbf55be483f358000,0xbf7bbf0e3f6d3ec4,0xbf0ebf7b3f353f80,0xbe48bf553ec43f6d,
0xbe89bf6a3ef13f7b,0x3e2fbf273d493f4e,0xbf65be603f460000,0xbf80bf1d3f783edb,0xbdfb3f31bdc9bf55,0xbf093ea13eacbf04,0x3f7f3f13bf75bec4,0x3f6f3f5fbf7dbf3e,
0x3f773ecfbf62be48,0x3f7c3f42bf80bf18,0xbee6bf7a3f223f80,0xbcc9bf4a3e793f67,0xbf7ebf393f7f3f0e,0xbf58bf733f713f5c,0x3d973f51be95bf6d,0xbeb83efc3e16bf2c,
0x3edbbf04be483f35,0x3f4ebd49bf223e95,0x3f2c3f7dbf55bf6d,0x3e793f71bef1bf7f,0x3eac3f78bf0ebf80,0xbe163f3ebdc9bf62,0xbf80bf183f7b3ec4,0xbf5cbf673f753f46,
0x3f673f5cbf7bbf35,0x3f183f80bf46bf75,0xbf3e3e163f0ebec4,0xbf78beac3f623dc9,0xbf71be793f558000,0xbf7dbf2c3f7f3ef1,0x3d49bf4e3e483f6d,0x3f04bedbbe953f22,
0x3f803ee6bf75be48,0x3f5f3f58bf78bf2c,0xbf13bf7e3f463f6d,0xbd97bf6a3eac3f7d,0xbeb83f273dc9bf55,0xbf4a3e2f3f18bedb,0x3f7a3e89bf620000,0x3f733f39bf80bf04,
0x3cc93f65be95bf7b,0xbefc3f093e79bf3e,0x3f51bdfbbf223ec4,0x3f7f3ecfbf71be16,0xbf6fbf423f7f3f0e,0xbf1dbf7c3f4e3f67,0x3e603f77bef1bf80,0xbea13f313d49bf5c,
0xbdc9bf753ec43f80,0x3ef1bf22be483f55,0x3f463f62bf6dbf35,0x3e953f7fbf0ebf7b,0xbf7fbe953f6d0000,0xbf62bf463f7b3f0e,0x3f22bef1bec43f35,0x3f753dc9bf553e48,
0x3f7f3e95bf6d8000,0x3f623f46bf7bbf0e,0xbf223ef13ec4bf35,0xbf75bdc93f55be48,0xbdc9bf753ec43f80,0x3ef1bf22be483f55,0x3f463f62bf6dbf35,0x3e953f7fbf0ebf7b,
0x3f58be89bf223f0e,0x3f7f3eb8bf78bd49,0xbf80bea13f750000,0xbf4abf513f713f18,0xbe2fbf7e3ef13f7b,0x3ee6bf39be163f67,0xbecf3f423dc9bf6d,0xbf5f3e603f2cbf04,
0x3f093f77bf46bf55,0xbd973f6fbe79bf80,0x3cc9bf733e953f80,0x3f1dbf13beac3f4e,0x3f7c3dfbbf623e48,0x3f653f31bf7dbedb,0xbf6abf273f7f3ec4,0xbefcbf7a3f3e3f5c,
0x3f183f67bf55bf35,0xbd493f78be95bf7f,0xbf5cbf2c3f7b3ec4,0xbeacbf7d3f223f62,0xbe163f71be48bf80,0xbf3e3f043ef1bf46,0xbe79bf803f0e3f6d,0x3edbbf4ebdc93f75,
0xbf4e3edb3f0ebf35,0xbf80be793f75bdc9,0x3f04bf3ebe483f6d,0x3f71be16bf463ef1,0xbf7dbeac3f7b8000,0xbf2cbf5c3f623f22,0x3f78bd49bf553ec4,0x3f673f18bf7fbe95,
0xbf733e603f46bf0e,0xbf6abefc3f803e16,0x3f7ebcc9bf623ec4,0x3f513f27bf78beac,0xbf7fbe2f3f75be48,0xbf31bf4a3f673f04,0x3f773eb8bf7f0000,0x3f093f65bf4ebf2c,
0xbea1bf7a3f223f55,0x3ecfbf5fbd493f7d,0x3dfb3f80bef1bf6d,0xbf133f423e79bf71,0x3d97bf7c3e953f7b,0x3f39bf1dbedb3f5c,0xbe893f6fbdc9bf80,0xbf583ee63f18bf3e,
0x3ec4bf6d00003f80,0x3f6dbec4bf353f35,0xbec43f6d0000bf80,0xbf6d3ec43f35bf35,0x3ec4bf6d00003f80,0x3f6dbec4bf353f35,0xbec43f6d0000bf80,0xbf6d3ec43f35bf35,
0x3f6d3ec4bf808000,0x3ec43f6dbf35bf35,0xbf6dbec43f808000,0xbec4bf6d3f353f35,0x3f6d3ec4bf808000,0x3ec43f6dbf35bf35,0xbf6dbec43f808000,0xbec4bf6d3f353f35,
0x3f423f13bf75be48,0x3cc93f7ebedbbf5c,0xbf5fbecf3f7f0000,0xbe60bf733f183f3e,0x3ee63f58bf46bf0e,0xbeb83f77bd49bf7d,0xbf1dbf393f623ec4,0x3e2fbf7f3e793f71,
0xbf273f513e95bf7b,0xbf803dfb3f67bf04,0x3efcbf6abdc93f80,0x3f7abea1bf4e3f2c,0xbf653f093f22bf55,0xbf6fbe893f80be16,0x3f4abf31bef13f6d,0x3f7c3d97bf783eac,
0xbf7d3eac3f55bf35,0xbf3ebf043f753dc9,0x3f783d49bf7b3ec4,0x3edb3f4ebf46bef1,0xbf183f673e48bf80,0xbf803e793f62bf22,0x3f5cbf2cbf0e3f6d,0x3f713e16bf7f3e95,
0xbe16bf713f0e3f35,0x3f2cbf5cbe953f7f,0xbe793f80be48bf6d,0xbf673f183f22bf62,0xbf4ebedb3f7b8000,0xbd49bf783ef13f46,0x3f043f3ebf55bec4,0xbeac3f7dbdc9bf75,
0x3f51bf4abef13f7b,0x3f733cc9bf7d3edb,0xbeb83f7fbdc9bf6d,0xbf773f093f3ebf5c,0xbe60bf5f3f223f0e,0x3f27bf6abe793f80,0x3f393ee6bf750000,0xbdfb3f7cbeacbf4e,
0x3f133f1dbf62be48,0xbea13f80be16bf67,0xbf6fbd973f7fbec4,0xbe89bf583f2c3f04,0x3f7abefcbf463f55,0x3f423ecfbf783d49,0xbf313f653e95bf80,0xbf7e3e2f3f71bf18,
0x3f46bf62bec43f80,0x3f75bdc9bf7b3f0e,0xbf7f3e953f6dbf35,0xbef1bf223f553e48,0x3f223ef1bf6d0000,0xbe953f7fbe48bf55,0x3dc9bf753ec43f35,0x3f62bf46bf0e3f7b,
0x3f223ef1bf6d8000,0xbe953f7fbe48bf55,0x3dc9bf753ec43f35,0x3f62bf46bf0e3f7b,0xbf463f623ec4bf80,0xbf753dc93f7bbf0e,0x3f7fbe95bf6d3f35,0x3ef13f22bf55be48,
0xbecf3f7fbdc9bf55,0xbf7e3f133f4ebf67,0xbf09befc3f620000,0x3ee6bf803d493f5c,0xbf31bea13f75be48,0x3e89bf7a3e793f3e,0x3f7cbf1dbf463f6d,0x3f273eb8bf713e16,
0xbf6a3d973f7fbf0e,0xbdfbbf513f183edb,0x3f58bf5fbef13f80,0x3f65bcc9bf803f04,0x3f39bf73be953f7b,0x3f77be60bf783f2c,0x3e2f3f4abf22bec4,0xbf423f6f3eacbf7d,
0x3eacbf783e483f35,0x3f7dbf2cbf463f75,0xbf803f183f55bf6d,0xbf04bedb3f62bdc9,0xbf673f5c3f0ebf80,0xbf4ebd493f7fbef1,0x3f3e3e16bf7b3ec4,0xbe793f71be95bf22,
0x3f71be79bf7b3f35,0x3e163f3ebf22be95,0xbd49bf4e3f0e3ec4,0x3f5cbf67bef13f7f,0xbedbbf043f558000,0x3f18bf80bdc93f62,0xbf2c3f7d3e48bf6d,0xbf783eac3f75bf46,
0xbf1d3f803dc9bf55,0xbf7a3ee63f71bf5c,0xbf27be2f3f75bec4,0x3ecfbf773e163f2c,0x3f5fbf6fbef13f7b,0x3f51bd97bf803f18,0x3ea13f09bf460000,0xbf393f7e3e79bf67,
0xbf4a3cc93f7fbf0e,0x3e60bf653eac3f04,0x3f42bf7cbe953f6d,0x3f6abe89bf7d3f3e,0x3efc3eb8bf623e48,0xbf133f7f3d49bf4e,0xbf733f583f22bf80,0xbf31bdfb3f78bedb,
0x3f7bbf55bf353f80,0x3f0e3e48bf6d3ec4,0xbe48bf0e3f350000,0x3f55bf7bbec43f6d,0xbf7b3f553f35bf80,0xbf0ebe483f6dbec4,0x3e483f0ebf350000,0xbf553f7b3ec4bf6d,
0x3e483f0ebf358000,0xbf553f7b3ec4bf6d,0x3f7bbf55bf353f80,0x3f0e3e48bf6d3ec4,0xbe48bf0e3f358000,0x3f55bf7bbec43f6d,0xbf7b3f553f35bf80,0xbf0ebe483f6dbec4,
0xbf7e3f313f62bf7b,0xbe60bee63f3ebe16,0xbd97bf133f220000,0x3f6abf77bf043f71,0x3f5fbeb8bf7f3f55,0xbe2f3f42bedbbe79,0xbea13f58be95bec4,0xbf803f4a3f4ebf80,
0x3dfbbf393ef13e48,0x3f7abf65bf2c3f7d,0x3f7fbf51bf463f80,0x3ecf3e89bf5c3eac,0xbefc3f6fbdc9bf0e,0xbf7c3f273f67bf78,0xbf733f093f75bf6d,0xbcc9bf1d3f183d49,
0x3f2cbe16bf7b3f35,0xbf043f67bdc9bef1,0x3f71bf78bf0e3f6d,0x3f18bd49bf753f22,0xbf803f4e3f55bf80,0xbe79beac3f46be95,0xbedb3f5cbe48bec4,0xbf7d3f3e3f62bf7f,
0xbf3e3f7d3e48bf35,0xbf5c3edb3f7fbf62,0x3eac3e79bf553ec4,0xbf4e3f803e95bf46,0x3d49bf183f0e8000,0x3f78bf71bf223f75,0xbf673f043f7bbf6d,0x3e16bf2c3ef13dc9,
0x3eb8bf423e953e48,0x3f7ebf51bf5c3f80,0x3f7abf77bf223f6d,0x3ee63cc9bf673f18,0x3f39bea1bf7f3f55,0xbefc3f58be16beac,0xbe2f3f1dbef10000,0xbf7f3f6a3f3ebf78,
0x3f6fbf27bf753f7b,0xbdfb3f13bf043d49,0x3e603e89bf463ec4,0xbf653f803edbbf4e,0xbf313f733dc9bf0e,0xbf5f3f093f7dbf71,0xbf7c3f4a3f62bf80,0xbd97becf3f2cbe79,
0x3f75bf46bf6d3f80,0xbdc93ef1bf0e3e48,0x3f62bf7fbec43f35,0x3f22be95bf7b3f55,0x3e95bf223ec40000,0x3f7fbf62bf553f7b,0xbef13dc93f6dbf35,0x3f46bf75be483f0e,
0xbe953f22bec48000,0xbf7f3f623f55bf7b,0x3ef1bdc9bf6d3f35,0xbf463f753e48bf0e,0x3f75bf46bf6d3f80,0xbdc93ef1bf0e3e48,0x3f62bf7fbec43f35,0x3f22be95bf7b3f55,
0xbe2fbdfb3f46bf0e,0x3f73bf80bf043f3e,0x3ecfbf273e950000,0x3f77bf58bf673f7d,0xbf7a3f5f3f62bf7b,0x3d97beb83f18beac,0xbf313ee63f7fbf6d,0x3f1dbf513d493e79,
0x3f7cbf7ebf223f55,0x3ea1bcc9bf5c3f2c,0x3f6abf42bf753f80,0xbe893f09bedb3e16,0x3e60befc3ef1be48,0x3f7fbf6fbf4e3f71,0x3f39bf65bdc93ec4,0x3f4abf13bf803f78,
0xbf783f803f0ebf35,0xbeac3e163f62bf46,0xbf4e3f673e48bec4,0xbf2c3f043f7fbf75,0xbf5c3f3e3f7bbf80,0x3edbbf183e95bdc9,0xbf7d3f713f55bf6d,0x3d49be793f22bef1,
0xbe793d493f55bf35,0x3f71bf7dbef13f22,0xbf183edb3f7bbf6d,0x3f3ebf5cbdc93e95,0x3f04bf2c3e488000,0x3f67bf4ebf753f7f,0x3e16beac3f0ebec4,0x3f80bf78bf463f62,
0xbd973e2fbf223f0e,0xbf803f7e3f3ebf4e,0xbe893eb8bef13ec4,0xbf7a3f733f5cbf67,0xbee63f09be953e48,0xbf6a3f5f3f71bf78,0xbf1d3f31bdc90000,0xbf513f423f7dbf80,
0xbf7f3f7c3f46bf55,0x3cc9bdfb3f2cbf18,0xbf773f6f3f62bf6d,0x3e60bea13f04bedb,0xbf653f583f75bf7b,0x3ecfbefc3eacbe79,0xbf4a3f393f7fbf80,0x3f13bf273e16bd49,
0xbf353f35bf803f80,0x3f35bf3500000000,0xbf353f35bf803f80,0x3f35bf3500000000,0xbf353f35bf803f80,0x3f35bf3500000000,0xbf353f35bf803f80,0x3f35bf3500000000,
0x3f35bf3580008000,0x3f35bf353f80bf80,0x3f35bf3580008000,0x3f35bf353f80bf80,0x3f35bf3580008000,0x3f35bf353f80bf80,0x3f35bf3580008000,0x3f35bf353f80bf80,
0xbf65bf583f623f55,0xbf6abf5f3f673f5c,0xbf4abf393f463f35,0xbf51bf423f4e3f3e,0xbf7fbf7c3f7f3f7b,0xbf80bf7e3f803f7d,0xbf77bf6f3f753f6d,0xbf7abf733f783f71,
0xbee6bf093ef13f0e,0xbecfbefc3edb3f04,0xbf1dbf313f223f35,0xbf13bf273f183f2c,0xbd97be2f3dc93e48,0xbcc9bdfb3d493e16,0xbe89beb83e953ec4,0xbe60bea13e793eac,
0xbf5cbf3e3f553f35,0xbf67bf4e3f623f46,0xbf7dbf713f7b3f6d,0xbf80bf783f7f3f75,0xbe79bd493e480000,0xbeacbe163e953dc9,0xbf18bedb3f0e3ec4,0xbf2cbf043f223ef1,
0xbf04bf2c3f0e3f35,0xbedbbf183ef13f22,0xbe16beac3e483ec4,0xbd49be793dc93e95,0xbf78bf803f7b3f80,0xbf71bf7d3f753f7f,0xbf4ebf673f553f6d,0xbf3ebf5c3f463f62,
0xbf7abf5f3f753f55,0xbf7fbf6f3f7d3f67,0xbf31bee63f223ec4,0xbf4abf133f3e3f04,0xbe2f3dfb3dc9be48,0xbea1bcc93e79bd49,0x3ecf3f27bef1bf35,0x3e893f09beacbf18,
0xbe60befc3e953f0e,0xbd97beb83e163edb,0xbf39bf653f463f6d,0xbf1dbf513f2c3f5c,0xbf7cbf7e3f7f3f7b,0xbf73bf803f783f80,0xbf6abf423f623f35,0xbf77bf583f713f4e,
0x3f623f7fbf6dbf80,0x3f463f75bf55bf7b,0x3e953f22bec4bf35,0x3dc93ef1be48bf0e,0xbef1bdc93ec40000,0xbf22be953f0e3e48,0xbf75bf463f6d3f35,0xbf7fbf623f7b3f55,
0xbef1bdc93ec48000,0xbf22be953f0e3e48,0xbf75bf463f6d3f35,0xbf7fbf623f7b3f55,0xbf62bf7f3f6d3f80,0xbf46bf753f553f7b,0xbe95bf223ec43f35,0xbdc9bef13e483f0e,
0x3f313f73bf46bf7b,0x3efc3f58bf18bf67,0x3f7c3f4abf75bf35,0x3f7f3f6abf80bf5c,0xbf6fbf273f623f0e,0xbf7ebf513f783f3e,0xbe603e893dc9bec4,0xbee63cc93eacbe16,
0xbf39bea13f223e48,0xbf5fbf093f4e3edb,0x3e2f3f1dbe95bf35,0xbd973ecfbd49bf04,0xbeb8bf423ef13f55,0xbdfbbf133e793f2c,0xbf7abf773f7f3f6d,0xbf65bf803f713f7d,
0x3d493f18be48bf35,0xbe793eac3dc9bef1,0xbf67bf043f553ec4,0xbf7dbf3e3f753f22,0x3f2c3e16bf0e0000,0x3f5c3edbbf46be95,0x3f713f78bf7bbf6d,0x3f4e3f80bf62bf7f,
0xbf80bf4e3f7b3f35,0xbf78bf713f7f3f62,0xbedbbf5c3f0e3f6d,0xbe16bf2c3e953f46,0x3f3e3f7dbf55bf80,0x3f043f67bf22bf75,0xbeac3e793e48bec4,0xbf18bd493ef1bdc9,
0xbf5fbeb83f463e48,0xbf7cbf273f713f04,0x3ea13f58bef1bf6d,0xbcc93f1dbe16bf3e,0x3f7e3f31bf75bf0e,0x3f7a3f65bf80bf4e,0x3d97bf133dc93f35,0x3ecfbe89be793edb,
0xbefcbf6f3f223f7b,0xbe2fbf423eac3f5c,0xbf73bf093f623ec4,0xbf80bf4a3f7d3f2c,0x3dfb3f39be95bf55,0xbe603ee63d49bf18,0x3f7f3f51bf7fbf35,0x3f6a3f77bf78bf67,
0xbf0ebf7b3f353f80,0xbe48bf553ec43f6d,0x3f553e48bf350000,0x3f7b3f0ebf6dbec4,0x3f0e3f7bbf35bf80,0x3e483f55bec4bf6d,0xbf55be483f350000,0xbf7bbf0e3f6d3ec4,
0x3f553e48bf358000,0x3f7b3f0ebf6dbec4,0x3f0e3f7bbf35bf80,0x3e483f55bec4bf6d,0xbf55be483f358000,0xbf7bbf0e3f6d3ec4,0xbf0ebf7b3f353f80,0xbe48bf553ec43f6d,
0x3efcbeb8be953f0e,0x3f513d97bf2c3e16,0xbf73bf583f7f3f35,0xbf39bf7e3f5c3f71,0xbf4abcc93f22be48,0xbf7abee63f673e79,0x3f423f7cbf62bf6d,0x3ecf3f77bf18bf80,
0x3f5f3f6fbf75bf55,0x3f133f7fbf3ebf7d,0x3ea1bf09bdc93f35,0x3f31bdfbbf043eac,0xbf1dbf803f463f7b,0xbe60bf653edb3f78,0xbf273e2f3ef1bec4,0xbf6abe893f4e3d49,
0x3f673f5cbf7bbf35,0x3f183f80bf46bf75,0xbf3e3e163f0ebec4,0xbf78beac3f623dc9,0xbf71be793f550000,0xbf7dbf2c3f7f3ef1,0x3d49bf4e3e483f6d,0x3f04bedbbe953f22,
0xbedb3f043e48bf35,0xbf4e3d493f22be95,0xbf2cbf7d3f553f6d,0xbe79bf713ef13f7f,0xbeacbf783f0e3f80,0x3e16bf3e3dc93f62,0x3f803f18bf7bbec4,0x3f5c3f67bf75bf46,
0xbf313ea13ef1bf0e,0xbf77be603f5cbd49,0x3f7c3f1dbf7fbec4,0x3f423f6fbf67bf4e,0xbecfbf7f3f223f7b,0x3dfbbf513e163f71,0xbf093efc3e95bf35,0xbf65bcc93f3ebe79,
0xbf39bf733f623f55,0xbe89bf7a3f043f80,0xbe2f3f4abdc9bf6d,0xbf273eb83edbbf18,0x3f6a3d97bf463e48,0x3f7e3f13bf7dbeac,0xbf58bf5f3f753f35,0xbee6bf803f2c3f78,
0x3dc93f75bec4bf80,0xbef13f223e48bf55,0xbf46bf623f6d3f35,0xbe95bf7f3f0e3f7b,0x3f7f3e95bf6d0000,0x3f623f46bf7bbf0e,0xbf223ef13ec4bf35,0xbf75bdc93f55be48,
0xbf7fbe953f6d8000,0xbf62bf463f7b3f0e,0x3f22bef1bec43f35,0x3f753dc9bf553e48,0x3dc93f75bec4bf80,0xbef13f223e48bf55,0xbf46bf623f6d3f35,0xbe95bf7f3f0e3f7b,
0xbf7abefc3f7f3e48,0xbf27bf6a3f5c3f3e,0x3f313f65bf62bf35,0x3dfb3f7cbedbbf7d,0xbf133f1d3e95bf55,0xbf733cc93f4ebeac,0x3f6fbd97bf463ec4,0x3f773f09bf80be79,
0x3e60bf5f3dc93f7b,0x3f42becfbf043f2c,0xbf393ee63ef1bf35,0xbf7ebe2f3f67be16,0xbf51bf4a3f753f0e,0xbea1bf803f183f71,0x3eb83f7fbf22bf6d,0xbe893f58bd49bf78,
0x3f4ebedbbf0e3f35,0x3f803e79bf753dc9,0xbf043f3e3e48bf6d,0xbf713e163f46bef1,0x3f7d3eacbf7b0000,0x3f2c3f5cbf62bf22,0xbf783d493f55bec4,0xbf67bf183f7f3e95,
0x3f183f67bf55bf35,0xbd493f78be95bf7f,0xbf5cbf2c3f7b3ec4,0xbeacbf7d3f223f62,0xbe163f71be48bf80,0xbf3e3f043ef1bf46,0xbe79bf803f0e3f6d,0x3edbbf4ebdc93f75,
0xbee63f583dc9bf7b,0xbf6f3e893f3ebf18,0x3f1dbf39be953f6d,0x3f7cbd97bf5c3edb,0xbf423f133ef1bf55,0xbf80bdfb3f71be79,0x3f5fbecfbf223f35,0x3f7a3ea1bf7d3d49,
0xbf65bf093f7f3e48,0xbeb8bf773f2c3f4e,0x3f4a3f31bf75bec4,0x3e2f3f7fbf04bf67,0xbf27bf513f623f0e,0x3cc9bf7e3eac3f78,0x3efc3f6abf46bf35,0xbe603f73be16bf80,
0x3ec4bf6d00003f80,0x3f6dbec4bf353f35,0xbec43f6d0000bf80,0xbf6d3ec43f35bf35,0x3ec4bf6d00003f80,0x3f6dbec4bf353f35,0xbec43f6d0000bf80,0xbf6d3ec43f35bf35,
0x3f6d3ec4bf808000,0x3ec43f6dbf35bf35,0xbf6dbec43f808000,0xbec4bf6d3f353f35,0x3f6d3ec4bf808000,0x3ec43f6dbf35bf35,0xbf6dbec43f808000,0xbec4bf6d3f353f35,
0x3d973f7cbef1bf55,0xbf313f4a3eacbf78,0xbe89bf6f3f223f35,0x3f09bf65be163f80,0xbea13f7abdc9bf7b,0xbf6a3efc3f2cbf4e,0x3dfbbf803e953f6d,0x3f51bf27bf043f67,
0xbf7f3e2f3f62bf0e,0xbf39bf1d3f713e79,0x3f77beb8bf463f35,0x3f583ee6bf7dbd49,0xbf73be603f7fbe48,0xbecfbf5f3f3e3f18,0x3f7e3cc9bf753ec4,0x3f133f42bf5cbedb,
0xbe16bf713f0e3f35,0x3f2cbf5cbe953f7f,0xbe793f80be48bf6d,0xbf673f183f22bf62,0xbf4ebedb3f7b0000,0xbd49bf783ef13f46,0x3f043f3ebf55bec4,0xbeac3f7dbdc9bf75,
0x3f7dbeacbf553f35,0x3f3e3f04bf75bdc9,0xbf78bd493f7bbec4,0xbedbbf4e3f463ef1,0x3f18bf67be483f80,0x3f80be79bf623f22,0xbf5c3f2c3f0ebf6d,0xbf71be163f7fbe95,
0xbe2f3f7ebe95bf55,0xbf653f313f18bf71,0xbecfbf423f463ec4,0x3efcbf7abd493f78,0x3f583e89bf7f3e48,0x3d973f6fbf04bf2c,0xbf803ea13f62bf35,0xbf1dbf133f673e16,
0xbf7c3dfb3f75bf0e,0xbee6bf393f4e3eac,0x3f6abf27bf223f6d,0x3f5f3e60bf803e79,0xbf093f773dc9bf7b,0xbf7f3eb83f5cbf3e,0xbcc9bf733ef13f35,0x3f4abf51bedb3f7d,
0xbf463f623ec4bf80,0xbf753dc93f7bbf0e,0x3f7fbe95bf6d3f35,0x3ef13f22bf55be48,0xbf22bef13f6d0000,0x3e95bf7f3e483f55,0xbdc93f75bec4bf35,0xbf623f463f0ebf7b,
0xbf22bef13f6d8000,0x3e95bf7f3e483f55,0xbdc93f75bec4bf35,0xbf623f463f0ebf7b,0x3f46bf62bec43f80,0x3f75bdc9bf7b3f0e,0xbf7f3e953f6dbf35,0xbef1bf223f553e48,
0x3f6fbf42bf223f7b,0x3f4a3e2fbf7d3eac,0xbe603f77be95bf35,0xbf733f393f2cbf78,0xbcc93f65bef1bf0e,0xbf5f3f583f04bf80,0xbf51bdfb3f7fbec4,0x3d97bf6a3edb3f18,
0x3eb83f27bf46be48,0xbf1d3f7c3e16bf71,0xbf7a3e893f75bf35,0xbea1bf313f3e3e79,0xbf803ee63f62bf55,0xbefcbf093f5c3d49,0x3f13bf7ebdc93f6d,0x3f7fbecfbf673f4e,
0xbf713e793f7bbf35,0xbe16bf3e3f223e95,0x3d493f4ebf0ebec4,0xbf5c3f673ef1bf7f,0x3edb3f04bf550000,0xbf183f803dc9bf62,0x3f2cbf7dbe483f6d,0x3f78beacbf753f46,
0x3eacbf783e483f35,0x3f7dbf2cbf463f75,0xbf803f183f55bf6d,0xbf04bedb3f62bdc9,0xbf673f5c3f0ebf80,0xbf4ebd493f7fbef1,0x3f3e3e16bf7b3ec4,0xbe793f71be95bf22,
0x3dfb3f31bf22be48,0xbf583f733edbbf78,0xbf7f3f133f62bf6d,0xbeb8befc3f4ebd49,0x3e89bf6a3e953f0e,0x3f7cbf42bf3e3f7d,0x3f65be60bf7f3f35,0xbcc93f4abf04beac,
0xbf7e3f393f46bf7b,0xbf09bea13f67be79,0x3d97bf513ef13ec4,0x3f6fbf5fbf183f80,0x3f77becfbf753f55,0x3e2f3f27bf2cbe16,0xbee63f7abdc9bf35,0xbf803f1d3f5cbf71,
0x3f7bbf55bf353f80,0x3f0e3e48bf6d3ec4,0xbe48bf0e3f350000,0x3f55bf7bbec43f6d,0xbf7b3f553f35bf80,0xbf0ebe483f6dbec4,0x3e483f0ebf350000,0xbf553f7b3ec4bf6d,
0x3e483f0ebf358000,0xbf553f7b3ec4bf6d,0x3f7bbf55bf353f80,0x3f0e3e48bf6d3ec4,0xbe48bf0e3f358000,0x3f55bf7bbec43f6d,0xbf7b3f553f35bf80,0xbf0ebe483f6dbec4,
0xbf1dbcc93f75bf0e,0x3f09bf733d493f18,0x3f27bf7cbdc93f35,0x3f6fbefcbf783f67,0x3e893ecfbf463e48,0xbf513f7f3eacbf5c,0xbf653f7a3ef1bf6d,0xbf393dfb3f7dbf2c,
0x3f4abf80be953f55,0x3f58bea1bf803f4e,0x3f42be2fbf7f3f35,0xbeb83f5fbe79bedb,0xbf773f6a3f22bf7b,0xbf13bd973f71bf04,0xbee6be603f62bec4,0x3f31bf7ebe163f3e,
0xbf3e3f7d3e48bf35,0xbf5c3edb3f7fbf62,0x3eac3e79bf553ec4,0xbf4e3f803e95bf46,0x3d49bf183f0e0000,0x3f78bf71bf223f75,0xbf673f043f7bbf6d,0x3e16bf2c3ef13dc9,
0xbf2c3e163f7bbf35,0x3f04bf673dc93ef1,0xbf713f783f0ebf6d,0xbf183d493f75bf22,0x3f80bf4ebf553f80,0x3e793eacbf463e95,0x3edbbf5c3e483ec4,0x3f7dbf3ebf623f7f,
0x3ecf3d97bf623f0e,0xbf4a3f7c3e79bf2c,0xbf093f5fbdc9bec4,0xbf733f313f71bf7d,0xbf803f653f46bf7b,0xbe89be603f4ebedb,0xbf133dfb3f75bf35,0x3f27bf6fbd493f04,
0xbf6a3f7f3ef1bf55,0xbf1d3e2f3f78bf3e,0xbf583efc3f7fbf6d,0x3ea1bf393eac3e16,0xbcc9bee63f22be48,0x3f77bf7abf183f67,0x3f51bf7ebe953f35,0x3f42beb8bf803f5c,
0xbf753f463f6dbf80,0x3dc9bef13f0ebe48,0xbf623f7f3ec4bf35,0xbf223e953f7bbf55,0xbe953f22bec40000,0xbf7f3f623f55bf7b,0x3ef1bdc9bf6d3f35,0xbf463f753e48bf0e,
0x3e95bf223ec48000,0x3f7fbf62bf553f7b,0xbef13dc93f6dbf35,0x3f46bf75be483f0e,0xbf753f463f6dbf80,0x3dc9bef13f0ebe48,0xbf623f7f3ec4bf35,0xbf223e953f7bbf55,
0xbf133f4abdc9be48,0xbf653f393f78bf80,0xbf6f3f7f3ef1bf35,0xbefc3e603f71bf4e,0x3f09be89bf753f55,0xbf423f6a3e16bedb,0xbcc93ea1bf223ec4,0xbf7e3f7c3f2cbf5c,
0xbf513f1d3f7fbf7b,0x3ee6bf313e793d49,0xbeb83d973f62bf35,0x3f5fbf7abeac3f18,0xbf583f773e95bf0e,0xbf273ecf3f7dbf67,0xbf803f733f46bf6d,0xbdfbbe2f3f3ebf04,
0x3e79bd49bf553f35,0xbf713f7d3ef1bf22,0x3f18bedbbf7b3f6d,0xbf3e3f5c3dc9be95,0xbf043f2cbe480000,0xbf673f4e3f75bf7f,0xbe163eacbf0e3ec4,0xbf803f783f46bf62,
0xbf783f803f0ebf35,0xbeac3e163f62bf46,0xbf4e3f673e48bec4,0xbf2c3f043f7fbf75,0xbf5c3f3e3f7bbf80,0x3edbbf183e95bdc9,0xbf7d3f713f55bf6d,0x3d49be793f22bef1,
0x3f27bf13bf7f3f7b,0xbf393f4a3d49be16,0x3efcbecfbf753f6d,0xbf583f653e79beac,0x3ea1be60bf623f55,0xbf6f3f773edbbf04,0x3dfbbcc9bf463f35,0xbf7c3f7f3f18bf2c,
0xbf423f513dc9be48,0xbf313f1d3f80bf7d,0xbf5f3f6a3e95bec4,0xbf093ee63f78bf71,0xbf733f7a3ef1bf0e,0xbeb83e893f67bf5c,0xbf7e3f803f22bf35,0xbe2f3d973f4ebf3e,
0x3f35bf35bf803f80,0xbf353f3500000000,0x3f35bf35bf803f80,0xbf353f3500000000,0x3f35bf35bf803f80,0xbf353f3500000000,0x3f35bf35bf803f80,0xbf353f3500000000,
0x3f35bf3580008000,0x3f35bf35bf803f80,0x3f35bf3580008000,0x3f35bf35bf803f80,0x3f35bf3580008000,0x3f35bf35bf803f80,0x3f35bf3580008000,0x3f35bf35bf803f80,
0x3ea13e603f753f7b,0xbeb8be89bf71bf78,0x3dfb3cc93f7f3f80,0xbe2fbd97bf7dbf80,0x3f273f133f463f55,0xbf31bf1dbf3ebf4e,0x3efc3ecf3f623f6d,0xbf09bee6bf5cbf67,
0x3f733f7abe95be48,0xbf6fbf773eac3e79,0x3f7e3f80bdc98000,0xbf7cbf7f3e163d49,0x3f423f51bf22bf0e,0xbf39bf4a3f2c3f18,0x3f5f3f6abef1bec4,0xbf58bf653f043edb,
0x3f5c3f3e3f0e3f35,0xbf67bf4ebef1bf22,0x3f7d3f713e483ec4,0xbf80bf78bdc9be95,0x3e793d493f7b3f80,0xbeacbe16bf75bf7f,0x3f183edb3f553f6d,0xbf2cbf04bf46bf62,
0x3f043f2cbf55bf35,0xbedbbf183f623f46,0x3e163eacbf7bbf6d,0xbd49be793f7f3f75,0x3f783f80be488000,0xbf71bf7d3e953dc9,0x3f4e3f67bf0ebec4,0xbf3ebf5c3f223ef1,
0x3f583f77bef1be48,0xbf42bf6a3f183eac,0x3f803f733dc93ec4,0xbf7ebf7c3d49be79,0x3f513f1d3f223f55,0xbf65bf39bf04bf3e,0x3eb83d973f753f80,0xbefcbe60bf67bf7d,
0xbf09be89bf62bf7b,0x3f273ecf3f4e3f71,0x3cc93ea1bf7fbf6d,0x3dfbbe2f3f803f78,0x3f133f4abf46bf0e,0xbee6bf313f5c3f2c,0x3f6f3f7fbe958000,0xbf5fbf7a3edb3e16,
0x3ef13dc93f6d3f80,0xbf22be95bf55bf7b,0x3f753f463ec43f35,0xbf7fbf62be48bf0e,0x3f623f7fbec40000,0xbf46bf753f0e3e48,0x3e953f22bf6dbf35,0xbdc9bef13f7b3f55,
0x3f623f7fbec48000,0xbf46bf753f0e3e48,0x3e953f22bf6dbf35,0xbdc9bef13f7b3f55,0xbef1bdc9bf6dbf80,0x3f223e953f553f7b,0xbf75bf46bec4bf35,0x3f7f3f623e483f0e,
0x3f803f653dc93f0e,0xbf77bf7a3e16beac,0x3f133dfb3f623f80,0xbf42beb8bf3ebf78,0xbecf3d97bf75bf7b,0x3f1d3e2f3f5c3f80,0x3f093f5fbf46bec4,0xbea1bf393f673f18,
0xbcc93ee6bf7fbf55,0x3e89be603f7d3f71,0x3f513f7ebef18000,0xbf27bf6f3f2c3e79,0xbf6abf7f3e95be48,0x3f4a3f7cbf04bd49,0xbf58befcbf22bf6d,0x3f733f313edb3f4e,
0x3d493f18bf7bbf35,0x3e79beac3f7f3f62,0xbf67bf04bf0ebf6d,0x3f7d3f3e3e953f46,0x3f2c3e163f553f80,0xbf5cbedbbf22bf75,0x3f713f78be483ec4,0xbf4ebf803ef1bdc9,
0xbf80bf4ebe48bf35,0x3f783f71bdc93ef1,0xbedbbf5c3f553ec4,0x3e163f2cbf75bf22,0x3f3e3f7dbf0e8000,0xbf04bf673f463e95,0xbeac3e79bf7bbf6d,0x3f183d493f623f7f,
0xbf77bf6a3dc9bf0e,0x3f513f7fbedb3e79,0xbee63e60bf75bf6d,0x3f393dfb3f4e3f80,0x3f4a3f80bef13e48,0xbf09bf733f3e3e16,0x3f423e2f3f463f80,0xbf6fbefcbf04bf71,
0x3e89becf3f7f3f55,0xbf133d97bf67bf78,0xbf65bf7a3e95bec4,0x3f313f7ebf183d49,0xbf1d3cc9bf62bf7b,0x3f583ea13f2c3f7d,0x3f273f7cbf228000,0xbeb8bf5f3f5c3eac,
0x3f553e483f353f80,0xbf7bbf0ebec4bf6d,0x3f0e3f7bbf350000,0xbe48bf553f6d3ec4,0xbf55be48bf35bf80,0x3f7b3f0e3ec43f6d,0xbf0ebf7b3f350000,0x3e483f55bf6dbec4,
0x3f0e3f7bbf358000,0xbe48bf553f6d3ec4,0xbf55be48bf35bf80,0x3f7b3f0e3ec43f6d,0xbf0ebf7b3f358000,0x3e483f55bf6dbec4,0x3f553e483f353f80,0xbf7bbf0ebec4bf6d,
0x3e893f6abf62be48,0x3e2fbf273f803f18,0x3f653e603f223f80,0xbf80bf1dbe79bf67,0x3dfbbf313f7f3f0e,0xbf093ea1bf71bf5c,0xbf7fbf13be95bf6d,0x3f6f3f5fbe163f2c,
0xbf77becfbef1bf7b,0x3f7c3f423d493f4e,0x3ee63f7abf468000,0xbcc9bf4a3f783edb,0x3f7e3f393dc93f55,0xbf58bf733eacbf04,0xbd97bf513f753ec4,0xbeb83efcbf7dbf3e,
0xbf67bf5c3e48bf35,0x3f183f80bf223e95,0x3f3ebe163f553f6d,0xbf78beacbef1bf7f,0x3f713e793f0e3f80,0xbf7dbf2cbdc9bf62,0xbd493f4ebf7bbec4,0x3f04bedb3f753f46,
0x3edbbf043f7b3f35,0xbf4e3d49bf46bf75,0x3f2c3f7dbf0e3ec4,0xbe79bf713f623dc9,0x3eac3f78bf558000,0x3e16bf3e3f7f3ef1,0xbf80bf18be48bf6d,0x3f5c3f67be953f22,
0x3f803ee63e953f7b,0xbf5fbf583e79bf3e,0xbf13bf7e3f22bec4,0x3d973f6abf71be16,0xbeb83f27bf7fbf0e,0x3f4abe2f3f4e3f67,0x3f7a3e893ef13f80,0xbf73bf393d49bf5c,
0x3cc93f65bf75be48,0x3efcbf093f783f2c,0x3f51bdfb3f463f6d,0xbf7fbecfbeacbf7d,0xbf6fbf423dc9bf55,0x3f1d3f7cbf183edb,0x3e603f77bf628000,0x3ea1bf313f803f04,
0x3f7f3e953ec43f80,0xbf62bf463e48bf55,0xbf223ef1bf6dbf35,0x3f753dc93f0e3f7b,0xbdc9bf753f6d0000,0xbef13f22bf7bbf0e,0x3f463f62bec43f35,0xbe95bf7f3f55be48,
0x3dc93f75bf6d8000,0x3ef1bf223f7b3f0e,0xbf46bf623ec4bf35,0x3e953f7fbf553e48,0x3f7f3e953ec43f80,0xbf62bf463e48bf55,0xbf223ef1bf6dbf35,0x3f753dc93f0e3f7b,
0xbf583e89bf46bf55,0x3f7f3eb83e793f80,0x3f803ea13e953f80,0xbf4abf513eacbf4e,0x3e2f3f7ebf623e48,0x3ee6bf393f7d3edb,0x3ecfbf423f7f3ec4,0xbf5f3e60bf3ebf5c,
0xbf09bf773f22bf0e,0xbd973f6fbf78bd49,0xbcc93f73bf758000,0x3f1dbf133f713f18,0xbf7cbdfbbef1bf7b,0x3f653f31be163f67,0x3f6a3f27bdc93f6d,0xbefcbf7a3f2cbf04,
0x3f4ebedb3f553f35,0xbf80be79be95bf7f,0xbf043f3ebf7bbec4,0x3f71be163f223f62,0x3f7d3eac3e483f80,0xbf2cbf5c3ef1bf46,0xbf783d49bf0ebf6d,0x3f673f18bdc93f75,
0x3f183f67bf0e3f35,0x3d49bf783f75bdc9,0xbf5cbf2c3e48bf6d,0x3eac3f7dbf463ef1,0xbe163f71bf7b8000,0x3f3ebf043f623f22,0xbe79bf803f55bec4,0xbedb3f4ebf7fbe95,
0xbf733e60bf22bf55,0x3f6a3efcbd493f7d,0x3f7ebcc93ef13f6d,0xbf51bf273e79bf71,0xbf7fbe2fbe95bf7b,0x3f313f4abedb3f5c,0x3f773eb83dc93f80,0xbf09bf653f18bf3e,
0xbea1bf7a3f46bf0e,0xbecf3f5fbf80be16,0x3dfb3f80bf623ec4,0x3f13bf423f783eac,0x3d97bf7c3f75be48,0xbf393f1dbf67bf04,0xbe893f6fbf7f8000,0x3f58bee63f4e3f2c,
0x3f6d3ec400003f80,0xbec4bf6d3f35bf35,0xbf6dbec40000bf80,0x3ec43f6dbf353f35,0x3f6d3ec400003f80,0xbec4bf6d3f35bf35,0xbf6dbec40000bf80,0x3ec43f6dbf353f35,
0xbec43f6dbf808000,0x3f6dbec43f353f35,0x3ec4bf6d3f808000,0xbf6d3ec4bf35bf35,0xbec43f6dbf808000,0x3f6dbec43f353f35,0x3ec4bf6d3f808000,0xbf6d3ec4bf35bf35,
0xbf42bf133e95bf7b,0x3cc93f7ebf673f04,0x3f5f3ecfbdc93f80,0xbe60bf733f4ebf2c,0xbee6bf583f22bf55,0xbeb83f77bf803e16,0x3f1d3f39bef13f6d,0x3e2fbf7f3f78beac,
0x3f27bf513f753e48,0xbf803dfbbedbbf5c,0xbefc3f6abf7f8000,0x3f7abea13f183f3e,0x3f65bf093f463f0e,0xbf6fbe89bd49bf7d,0xbf4a3f31bf62bec4,0x3f7c3d973e793f71,
0x3e163f71bf553f35,0x3f2cbf5c3f753dc9,0x3e79bf803f7bbec4,0xbf673f18bf46bef1,0x3f4e3edbbe483f80,0xbd49bf783f62bf22,0xbf04bf3e3f0ebf6d,0xbeac3f7dbf7f3e95,
0xbf7d3eacbf0ebf35,0x3f3e3f04be953f7f,0x3f783d493e483f6d,0xbedbbf4e3f22bf62,0xbf183f67bf7b8000,0x3f80be793ef13f46,0x3f5cbf2c3f553ec4,0xbf71be16bdc9bf75,
0x3f51bf4a3f623e48,0xbf73bcc9be16bf67,0xbeb83f7fbf7f3ec4,0x3f77bf093f2c3f04,0xbe60bf5f3f46bf55,0xbf273f6abf783d49,0x3f393ee6be953f80,0x3dfbbf7c3f71bf18,
0x3f133f1dbef13f7b,0x3ea1bf803f7dbedb,0xbf6fbd97bdc9bf6d,0x3e893f58bf3e3f5c,0x3f7abefc3f223f0e,0xbf42becf3e79bf80,0xbf313f65bf758000,0x3f7ebe2f3eac3f4e,
0x3f223ef1bec43f80,0x3e95bf7f3f7bbf0e,0x3dc9bf753f6dbf35,0xbf623f46bf55be48,0xbf463f62bf6d0000,0x3f75bdc93e483f55,0x3f7fbe953ec43f35,0xbef1bf223f0ebf7b,
0xbf463f62bf6d8000,0x3f75bdc93e483f55,0x3f7fbe953ec43f35,0xbef1bf223f0ebf7b,0xbf22bef13ec4bf80,0xbe953f7fbf7b3f0e,0xbdc93f75bf6d3f35,0x3f62bf463f553e48,
0x3ecfbf7f3f7fbf0e,0xbf7e3f13bf18bedb,0x3f093efcbef13f80,0x3ee6bf803f80bf04,0x3f313ea1be953f7b,0x3e89bf7a3f78bf2c,0xbf7c3f1dbf22bec4,0x3f273eb8beac3f7d,
0x3f6abd973dc93f55,0xbdfbbf513f4ebf67,0xbf583f5fbf628000,0x3f65bcc93d493f5c,0xbf393f73bf753e48,0x3f77be603e793f3e,0xbe2fbf4a3f46bf6d,0xbf423f6fbf713e16,
0xbf713e79be48bf35,0x3e163f3ebf463f75,0x3d493f4ebf553f6d,0x3f5cbf673f62bdc9,0x3edb3f04bf0e3f80,0x3f18bf803f7fbef1,0x3f2cbf7d3f7bbec4,0xbf783eacbe95bf22,
0x3eacbf783f7bbf35,0xbf7d3f2cbf22be95,0xbf803f18bf0ebec4,0x3f043edbbef13f7f,0xbf673f5cbf558000,0x3f4e3d49bdc93f62,0x3f3e3e16be483f6d,0x3e79bf713f75bf46,
0xbf1d3f80bf7f3f0e,0x3f7abee63eac3f04,0xbf27be2f3e95bf6d,0xbecf3f77bf7d3f3e,0x3f5fbf6f3f62be48,0xbf513d973d49bf4e,0x3ea13f09bf223f80,0x3f39bf7e3f78bedb,
0xbf4a3cc93dc9bf55,0xbe603f65bf713f5c,0x3f42bf7c3f75bec4,0xbf6a3e89be16bf2c,0x3efc3eb8bef13f7b,0x3f13bf7f3f80bf18,0xbf733f58bf468000,0x3f313dfbbe793f67,
0x3e483f0ebf353f80,0x3f55bf7b3f6dbec4,0x3f7bbf553f350000,0xbf0ebe483ec4bf6d,0xbe48bf0e3f35bf80,0xbf553f7bbf6d3ec4,0xbf7b3f55bf350000,0x3f0e3e48bec43f6d,
0xbf7b3f55bf358000,0x3f0e3e48bec43f6d,0x3e483f0ebf353f80,0x3f55bf7b3f6dbec4,0x3f7bbf553f358000,0xbf0ebe483ec4bf6d,0xbe48bf0e3f35bf80,0xbf553f7bbf6d3ec4,
0x3f7ebf313ef13e48,0xbe60bee63f2cbf7d,0x3d973f13bf463f80,0x3f6abf773f5cbeac,0xbf5f3eb8bdc9bf0e,0xbe2f3f42bf673f78,0x3ea1bf583f75bf6d,0xbf803f4abf18bd49,
0xbdfb3f39bf623f7b,0x3f7abf653f3ebe16,0xbf7f3f51bf228000,0x3ecf3e89bf043f71,0x3efcbf6f3f7fbf55,0xbf7c3f27bedbbe79,0x3f73bf093e953ec4,0xbcc9bf1d3f4ebf80,
0x3f3ebf7d3f7bbf35,0xbf5c3edbbdc9bef1,0xbeacbe793f0ebf6d,0xbf4e3f80bf753f22,0xbd493f18bf553f80,0x3f78bf713f46be95,0x3f67bf043e483ec4,0x3e16bf2c3f62bf7f,
0x3f2cbe16be483f35,0x3f04bf673f7fbf62,0x3f71bf783f55bec4,0xbf183d493e95bf46,0xbf803f4ebf0e8000,0x3e793eacbf223f75,0xbedb3f5cbf7b3f6d,0x3f7dbf3e3ef13dc9,
0x3eb8bf423f75bf7b,0xbf7e3f51bf043d49,0x3f7abf773f46bec4,0xbee6bcc93edbbf4e,0x3f39bea1bdc93f0e,0x3efcbf583f7dbf71,0xbe2f3f1dbf623f80,0x3f7fbf6a3f2cbe79,
0x3f6fbf273e953e48,0x3dfbbf133f5cbf80,0x3e603e89bf223f6d,0x3f65bf803f67bf18,0xbf313f73bf7f3f55,0x3f5fbf093e163eac,0xbf7c3f4abef18000,0x3d973ecfbf3e3f78,
0xbe953f22bf6d3f80,0x3f7fbf623f0ebe48,0x3ef1bdc9bec43f35,0x3f46bf753f7bbf55,0x3f75bf463ec40000,0x3dc9bef13f55bf7b,0x3f62bf7f3f6dbf35,0xbf223e953e48bf0e,
0xbf753f46bec48000,0xbdc93ef1bf553f7b,0xbf623f7fbf6d3f35,0x3f22be95be483f0e,0xbe953f22bf6d3f80,0x3f7fbf623f0ebe48,0x3ef1bdc9bec43f35,0x3f46bf753f7bbf55,
0x3e2f3dfbbf223f55,0x3f73bf803f5cbf2c,0xbecf3f27bf753f80,0x3f77bf583edbbe16,0x3f7abf5f3ef1be48,0x3d97beb83f4ebf71,0x3f31bee6bdc93ec4,0x3f1dbf513f80bf78,
0xbf7c3f7ebf463f0e,0x3ea1bcc9bf043f3e,0xbf6a3f42be958000,0xbe893f09bf673f7d,0xbe603efcbf623f7b,0x3f7fbf6f3f18beac,0xbf393f65bf7f3f6d,0x3f4abf133d493e79,
0x3e79bd49bf0e3f35,0x3f71bf7d3f62bf46,0x3f18bedbbe483ec4,0x3f3ebf5c3f7fbf75,0xbf043f2cbf7b3f80,0x3f67bf4e3e95bdc9,0xbe163eacbf553f6d,0x3f80bf783f22bef1,
0xbf783f80bf553f35,0x3eacbe16bef13f22,0xbf4e3f67bf7b3f6d,0x3f2cbf04bdc93e95,0xbf5c3f3ebe488000,0xbedb3f18bf753f7f,0xbf7d3f71bf0e3ec4,0xbd493e79bf463f62,
0xbd973e2fbf463f55,0x3f80bf7e3f2cbf18,0xbe893eb8bf623f6d,0x3f7abf733f04bedb,0xbee63f09bf753f7b,0x3f6abf5f3eacbe79,0xbf1d3f31bf7f3f80,0x3f51bf423e16bd49,
0xbf7f3f7cbf223f0e,0xbcc93dfbbf3e3f4e,0xbf773f6fbef13ec4,0xbe603ea1bf5c3f67,0xbf653f58be953e48,0xbecf3efcbf713f78,0xbf4a3f39bdc98000,0xbf133f27bf7d3f80,
0x3f35bf35bf803f80,0xbf353f3500000000,0x3f35bf35bf803f80,0xbf353f3500000000,0x3f35bf35bf803f80,0xbf353f3500000000,0x3f35bf35bf803f80,0xbf353f3500000000,
0x3f35bf3580008000,0x3f35bf35bf803f80,0x3f35bf3580008000,0x3f35bf35bf803f80,0x3f35bf3580008000,0x3f35bf35bf803f80,0x3f35bf3580008000,0x3f35bf35bf803f80,
0x3f653f583ef13f0e,0xbf6abf5fbedbbf04,0x3f4a3f393f223f35,0xbf51bf42bf18bf2c,0x3f7f3f7c3dc93e48,0xbf80bf7ebd49be16,0x3f773f6f3e953ec4,0xbf7abf73be79beac,
0x3ee63f09bf62bf55,0xbecfbefc3f673f5c,0x3f1d3f31bf46bf35,0xbf13bf273f4e3f3e,0x3d973e2fbf7fbf7b,0xbcc9bdfb3f803f7d,0x3e893eb8bf75bf6d,0xbe60bea13f783f71,
0x3f043f2cbf55bf35,0xbedbbf183f623f46,0x3e163eacbf7bbf6d,0xbd49be793f7f3f75,0x3f783f80be480000,0xbf71bf7d3e953dc9,0x3f4e3f67bf0ebec4,0xbf3ebf5c3f223ef1,
0xbf5cbf3ebf0ebf35,0x3f673f4e3ef13f22,0xbf7dbf71be48bec4,0x3f803f783dc93e95,0xbe79bd49bf7bbf80,0x3eac3e163f753f7f,0xbf18bedbbf55bf6d,0x3f2c3f043f463f62,
0xbf7abf5fbe95bf0e,0x3f7f3f6f3e163edb,0xbf31bee6bf46bf6d,0x3f4a3f133f2c3f5c,0xbe2f3dfbbf7fbf7b,0x3ea13cc93f783f80,0x3ecf3f27bf62bf35,0xbe89bf093f713f4e,
0xbe60befc3f753f55,0x3d973eb8bf7dbf67,0xbf39bf653f223ec4,0x3f1d3f51bf3ebf04,0xbf7cbf7e3dc9be48,0x3f733f80be793d49,0xbf6abf42bef1bf35,0x3f773f583eac3f18,
0xbef1bdc9bf6dbf80,0x3f223e953f553f7b,0xbf75bf46bec4bf35,0x3f7f3f623e483f0e,0xbf62bf7f3ec40000,0x3f463f75bf0ebe48,0xbe95bf223f6d3f35,0x3dc93ef1bf7bbf55,
0xbf62bf7f3ec48000,0x3f463f75bf0ebe48,0xbe95bf223f6d3f35,0x3dc93ef1bf7bbf55,0x3ef13dc93f6d3f80,0xbf22be95bf55bf7b,0x3f753f463ec43f35,0xbf7fbf62be48bf0e,
0xbf31bf733f223e48,0x3efc3f58bf4ebedb,0xbf7cbf4abe95bf35,0x3f7f3f6a3d493f04,0x3f6f3f273ef13f55,0xbf7ebf51be79bf2c,0x3e60be893f7f3f6d,0xbee63cc9bf71bf7d,
0x3f393ea13f463f7b,0xbf5fbf09bf18bf67,0xbe2fbf1d3f753f35,0xbd973ecfbf80bf5c,0x3eb83f42bf62bf0e,0xbdfbbf133f783f3e,0x3f7a3f77bdc93ec4,0xbf65bf803eacbe16,
0x3f803f4e3e483f35,0xbf78bf713dc9bef1,0x3edb3f5cbf55bec4,0xbe16bf2c3f753f22,0xbf3ebf7d3f0e0000,0x3f043f67bf46be95,0x3eacbe793f7b3f6d,0xbf18bd49bf62bf7f,
0x3d493f18bf7bbf35,0x3e79beac3f7f3f62,0xbf67bf04bf0ebf6d,0x3f7d3f3e3e953f46,0x3f2c3e163f553f80,0xbf5cbedbbf22bf75,0x3f713f78be483ec4,0xbf4ebf803ef1bdc9,
0xbf5fbeb8bf22bf7b,0x3f7c3f273eac3f5c,0x3ea13f58bf62bec4,0x3cc9bf1d3f7d3f2c,0x3f7e3f313e953f55,0xbf7abf653d49bf18,0x3d97bf133f7f3f35,0xbecf3e89bf78bf67,
0xbefcbf6f3f463e48,0x3e2f3f42bf71bf04,0xbf73bf09bef1bf6d,0x3f803f4a3e163f3e,0x3dfb3f39bf75bf0e,0x3e60bee63f803f4e,0x3f7f3f513dc93f35,0xbf6abf773e79bedb,
0x3f553e483f353f80,0xbf7bbf0ebec4bf6d,0x3f0e3f7bbf350000,0xbe48bf553f6d3ec4,0xbf55be48bf35bf80,0x3f7b3f0e3ec43f6d,0xbf0ebf7b3f350000,0x3e483f55bf6dbec4,
0x3f0e3f7bbf358000,0xbe48bf553f6d3ec4,0xbf55be48bf35bf80,0x3f7b3f0e3ec43f6d,0xbf0ebf7b3f358000,0x3e483f55bf6dbec4,0x3f553e483f353f80,0xbf7bbf0ebec4bf6d,
0xbefc3eb8bf75bf55,0x3f513d973f3e3f7d,0x3f733f58bdc93f35,0xbf39bf7e3f04beac,0x3f4a3cc93f463f7b,0xbf7abee6bedbbf78,0xbf42bf7c3ef1bec4,0x3ecf3f77bf4ebd49,
0xbf5fbf6f3e95bf0e,0x3f133f7fbf2c3e16,0xbea13f09bf7fbf35,0x3f31bdfb3f5c3f71,0x3f1d3f80bf223e48,0xbe60bf653f673e79,0x3f27be2f3f623f6d,0xbf6abe89bf18bf80,
0x3edbbf043f7b3f35,0xbf4e3d49bf46bf75,0x3f2c3f7dbf0e3ec4,0xbe79bf713f623dc9,0x3eac3f78bf550000,0x3e16bf3e3f7f3ef1,0xbf80bf18be48bf6d,0x3f5c3f67be953f22,
0x3f673f5cbe483f35,0xbf18bf803f22be95,0xbf3e3e16bf55bf6d,0x3f783eac3ef13f7f,0xbf71be79bf0ebf80,0x3f7d3f2c3dc93f62,0x3d49bf4e3f7b3ec4,0xbf043edbbf75bf46,
0xbf313ea1bf62bf55,0x3f773e603f043f80,0x3f7c3f1d3dc93f6d,0xbf42bf6f3edbbf18,0xbecfbf7f3f46be48,0xbdfb3f51bf7dbeac,0xbf093efcbf75bf35,0x3f653cc93f2c3f78,
0xbf39bf733ef1bf0e,0x3e893f7abf5c3d49,0xbe2f3f4abf7fbec4,0x3f27beb83f673f4e,0x3f6a3d973f223f7b,0xbf7ebf13be16bf71,0xbf58bf5f3e95bf35,0x3ee63f80bf3e3e79,
0xbf7fbe95bec4bf80,0x3f623f46be483f55,0x3f22bef13f6d3f35,0xbf75bdc9bf0ebf7b,0x3dc93f75bf6d0000,0x3ef1bf223f7b3f0e,0xbf46bf623ec4bf35,0x3e953f7fbf553e48,
0xbdc9bf753f6d8000,0xbef13f22bf7bbf0e,0x3f463f62bec43f35,0xbe95bf7f3f55be48,0xbf7fbe95bec4bf80,0x3f623f46be483f55,0x3f22bef13f6d3f35,0xbf75bdc9bf0ebf7b,
0x3f7a3efc3dc93f7b,0xbf27bf6a3f04bf2c,0xbf31bf653ef1bf35,0x3dfb3f7cbf673e16,0x3f13bf1d3f753f0e,0xbf733cc9bf18bf71,0xbf6f3d97bf22bf6d,0x3f773f093d493f78,
0xbe603f5fbf7fbe48,0x3f42becf3f5c3f3e,0x3f39bee63f623f35,0xbf7ebe2fbedbbf7d,0x3f513f4abe953f55,0xbea1bf803f4ebeac,0xbeb8bf7f3f46bec4,0xbe893f58bf80be79,
0xbf18bf673f0ebf35,0xbd493f78bf753dc9,0x3f5c3f2cbe483f6d,0xbeacbf7d3f46bef1,0x3e16bf713f7b0000,0xbf3e3f04bf62bf22,0x3e793f80bf553ec4,0x3edbbf4e3f7f3e95,
0x3f4ebedb3f553f35,0xbf80be79be95bf7f,0xbf043f3ebf7bbec4,0x3f71be163f223f62,0x3f7d3eac3e483f80,0xbf2cbf5c3ef1bf46,0xbf783d49bf0ebf6d,0x3f673f18bdc93f75,
0xbee63f58bf7fbe48,0x3f6fbe893f2c3f4e,0x3f1dbf393f753ec4,0xbf7c3d97bf04bf67,0xbf423f13bf62bf0e,0x3f803dfb3eac3f78,0x3f5fbecf3f463f35,0xbf7abea1be16bf80,
0xbf65bf093dc9bf7b,0x3eb83f77bf3e3f18,0x3f4a3f31be953f6d,0xbe2fbf7f3f5cbedb,0xbf27bf513ef1bf55,0xbcc93f7ebf713e79,0x3efc3f6abf223f35,0x3e60bf733f7dbd49,
0x3f6d3ec400003f80,0xbec4bf6d3f35bf35,0xbf6dbec40000bf80,0x3ec43f6dbf353f35,0x3f6d3ec400003f80,0xbec4bf6d3f35bf35,0xbf6dbec40000bf80,0x3ec43f6dbf353f35,
0xbec43f6dbf808000,0x3f6dbec43f353f35,0x3ec4bf6d3f808000,0xbf6d3ec4bf35bf35,0xbec43f6dbf808000,0x3f6dbec43f353f35,0x3ec4bf6d3f808000,0xbf6d3ec4bf35bf35,
0xbd97bf7c3f62bf0e,0xbf313f4abf71be79,0x3e893f6fbf463f35,0x3f09bf653f7d3d49,0x3ea1bf7a3f7fbe48,0xbf6a3efcbf3ebf18,0xbdfb3f80bf753ec4,0x3f51bf273f5c3edb,
0x3f7fbe2f3ef13f55,0xbf39bf1d3eacbf78,0xbf773eb8bf22bf35,0x3f583ee6be163f80,0x3f733e603dc93f7b,0xbecfbf5f3f2cbf4e,0xbf7ebcc9be95bf6d,0x3f133f42bf043f67,
0xbf7d3eacbf0ebf35,0x3f3e3f04be953f7f,0x3f783d493e483f6d,0xbedbbf4e3f22bf62,0xbf183f67bf7b0000,0x3f80be793ef13f46,0x3f5cbf2c3f553ec4,0xbf71be16bdc9bf75,
0xbe16bf713f55bf35,0xbf2c3f5cbf75bdc9,0xbe793f80bf7b3ec4,0x3f67bf183f463ef1,0xbf4ebedb3e48bf80,0x3d493f78bf623f22,0x3f043f3ebf0e3f6d,0x3eacbf7d3f7fbe95,
0xbe2f3f7ebf753f0e,0x3f65bf313f4e3eac,0xbecfbf423f22bf6d,0xbefc3f7abf803e79,0x3f583e89bdc93f7b,0xbd97bf6f3f5cbf3e,0xbf803ea1bef1bf35,0x3f1d3f13bedb3f7d,
0xbf7c3dfbbe95bf55,0x3ee63f39bf183f71,0x3f6abf273f463ec4,0xbf5fbe603d49bf78,0xbf093f77bf7f3e48,0x3f7fbeb83f043f2c,0xbcc9bf733f62bf35,0xbf4a3f51bf67be16,
0xbf22bef13ec4bf80,0xbe953f7fbf7b3f0e,0xbdc93f75bf6d3f35,0x3f62bf463f553e48,0x3f46bf623f6d0000,0xbf753dc9be48bf55,0xbf7f3e95bec4bf35,0x3ef13f22bf0e3f7b,
0x3f46bf623f6d8000,0xbf753dc9be48bf55,0xbf7f3e95bec4bf35,0x3ef13f22bf0e3f7b,0x3f223ef1bec43f80,0x3e95bf7f3f7bbf0e,0x3dc9bf753f6dbf35,0xbf623f46bf55be48,
0xbf6f3f42bf46be48,0x3f4a3e2fbe163f71,0x3e60bf773f75bf35,0xbf733f39bf3ebe79,0x3cc9bf653f62bf55,0xbf5f3f58bf5cbd49,0x3f513dfbbdc93f6d,0x3d97bf6a3f67bf4e,
0xbeb8bf273f22bf7b,0xbf1d3f7cbf7d3eac,0x3f7abe893e953f35,0xbea1bf313f2cbf78,0x3f80bee63ef13f0e,0xbefcbf093f04bf80,0xbf133f7ebf7f3ec4,0x3f7fbecf3edb3f18,
0xbeac3f78bf7b3f35,0x3f7dbf2c3f223e95,0x3f80bf183f0e3ec4,0xbf04bedb3ef1bf7f,0x3f67bf5c3f550000,0xbf4ebd493dc9bf62,0xbf3ebe163e48bf6d,0xbe793f71bf753f46,
0xbf713e79be48bf35,0x3e163f3ebf463f75,0x3d493f4ebf553f6d,0x3f5cbf673f62bdc9,0x3edb3f04bf0e3f80,0x3f18bf803f7fbef1,0x3f2cbf7d3f7bbec4,0xbf783eacbe95bf22,
0x3dfb3f31bf463f7b,0x3f58bf733f67be79,0xbf7f3f13bef1bec4,0x3eb83efcbf183f80,0x3e89bf6a3f75bf55,0xbf7c3f42bf2cbe16,0x3f65be603dc93f35,0x3cc9bf4a3f5cbf71,
0xbf7e3f39bf22be48,0x3f093ea1bedb3f78,0x3d97bf513f62bf6d,0xbf6f3f5fbf4e3d49,0x3f77becf3e953f0e,0xbe2fbf273f3ebf7d,0xbee63f7abf7f3f35,0x3f80bf1d3f043eac,
0x3e483f0ebf353f80,0x3f55bf7b3f6dbec4,0x3f7bbf553f350000,0xbf0ebe483ec4bf6d,0xbe48bf0e3f35bf80,0xbf553f7bbf6d3ec4,0xbf7b3f55bf350000,0x3f0e3e48bec43f6d,
0xbf7b3f55bf358000,0x3f0e3e48bec43f6d,0x3e483f0ebf353f80,0x3f55bf7b3f6dbec4,0x3f7bbf553f358000,0xbf0ebe483ec4bf6d,0xbe48bf0e3f35bf80,0xbf553f7bbf6d3ec4,
0x3f1d3cc9be953f55,0x3f09bf733f80bf4e,0xbf273f7cbf7f3f35,0x3f6fbefc3e793edb,0xbe89becf3f22bf7b,0xbf513f7fbf713f04,0x3f65bf7a3f62bec4,0xbf393dfb3e16bf3e,
0xbf4a3f80bf753f0e,0x3f58bea13d493f18,0xbf423e2f3dc9bf35,0xbeb83f5fbf783f67,0x3f77bf6a3f46be48,0xbf13bd973eacbf5c,0x3ee63e60bef13f6d,0x3f31bf7e3f7dbf2c,
0x3f2cbe16be483f35,0x3f04bf673f7fbf62,0x3f71bf783f55bec4,0xbf183d493e95bf46,0xbf803f4ebf0e0000,0x3e793eacbf223f75,0xbedb3f5cbf7b3f6d,0x3f7dbf3e3ef13dc9,
0xbf3e3f7dbf7b3f35,0x3f5cbedb3dc93ef1,0x3eac3e79bf0e3f6d,0x3f4ebf803f75bf22,0x3d49bf183f55bf80,0xbf783f71bf463e95,0xbf673f04be48bec4,0xbe163f2cbf623f7f,
0x3ecf3d97bef13f55,0x3f4abf7c3f78bf3e,0xbf093f5fbf7f3f6d,0x3f73bf313eac3e16,0xbf803f65bf223e48,0x3e893e60bf183f67,0xbf133dfb3e95bf35,0xbf273f6fbf803f5c,
0xbf6a3f7fbf623f0e,0x3f1dbe2fbe793f2c,0xbf583efcbdc9bec4,0xbea13f39bf713f7d,0xbcc9bee63f46bf7b,0xbf773f7abf4e3edb,0x3f51bf7e3f75bf35,0xbf423eb83d49bf04,
0x3e95bf223f6dbf80,0xbf7f3f62bf0e3e48,0xbef13dc93ec4bf35,0xbf463f75bf7b3f55,0xbf753f46bec40000,0xbdc93ef1bf553f7b,0xbf623f7fbf6d3f35,0x3f22be95be483f0e,
0x3f75bf463ec48000,0x3dc9bef13f55bf7b,0x3f62bf7f3f6dbf35,0xbf223e953e48bf0e,0x3e95bf223f6dbf80,0xbf7f3f62bf0e3e48,0xbef13dc93ec4bf35,0xbf463f75bf7b3f55,
0x3f13bf4a3f7fbf7b,0xbf653f39be79bd49,0x3f6fbf7f3f62bf35,0xbefc3e603eacbf18,0xbf093e893e95bf0e,0xbf423f6abf7d3f67,0x3cc9bea13f46bf6d,0xbf7e3f7cbf3e3f04,
0x3f51bf1d3dc93e48,0x3ee6bf313f78bf80,0x3eb8bd97bef13f35,0x3f5fbf7a3f71bf4e,0x3f58bf773f75bf55,0xbf273ecf3e16bedb,0x3f80bf733f22bec4,0xbdfbbe2f3f2cbf5c,
0x3f78bf803f55bf35,0xbeac3e163ef1bf22,0x3f4ebf673f7bbf6d,0xbf2c3f043dc9be95,0x3f5cbf3e3e480000,0x3edbbf183f75bf7f,0x3f7dbf713f0ebec4,0x3d49be793f46bf62,
0x3e79bd49bf0e3f35,0x3f71bf7d3f62bf46,0x3f18bedbbe483ec4,0x3f3ebf5c3f7fbf75,0xbf043f2cbf7b3f80,0x3f67bf4e3e95bdc9,0xbe163eacbf553f6d,0x3f80bf783f22bef1,
0x3f27bf13bdc93e48,0x3f39bf4a3f80bf7d,0x3efcbecfbe953ec4,0x3f58bf653f78bf71,0x3ea1be60bef13f0e,0x3f6fbf773f67bf5c,0x3dfbbcc9bf223f35,0x3f7cbf7f3f4ebf3e,
0xbf423f51bf7f3f7b,0x3f31bf1dbd493e16,0xbf5f3f6abf753f6d,0x3f09bee6be793eac,0xbf733f7abf623f55,0x3eb8be89bedb3f04,0xbf7e3f80bf463f35,0x3e2fbd97bf183f2c,
0x3f35bf35bf803f80,0xbf353f3500000000,0x3f35bf35bf803f80,0xbf353f3500000000,0x3f35bf35bf803f80,0xbf353f3500000000,0x3f35bf35bf803f80,0xbf353f3500000000,
0x3f35bf3580008000,0x3f35bf35bf803f80,0x3f35bf3580008000,0x3f35bf35bf803f80,0x3f35bf3580008000,0x3f35bf35bf803f80,0x3f35bf3580008000,0x3f35bf35bf803f80,
0x3f733f7abe95be48,0xbf6fbf773eac3e79,0x3f7e3f80bdc90000,0xbf7cbf7f3e163d49,0x3f423f51bf22bf0e,0xbf39bf4a3f2c3f18,0x3f5f3f6abef1bec4,0xbf58bf653f043edb,
0xbea1be60bf75bf7b,0x3eb83e893f713f78,0xbdfbbcc9bf7fbf80,0x3e2f3d973f7d3f80,0xbf27bf13bf46bf55,0x3f313f1d3f3e3f4e,0xbefcbecfbf62bf6d,0x3f093ee63f5c3f67,
0xbf5cbf3ebf0ebf35,0x3f673f4e3ef13f22,0xbf7dbf71be48bec4,0x3f803f783dc93e95,0xbe79bd49bf7bbf80,0x3eac3e163f753f7f,0xbf18bedbbf55bf6d,0x3f2c3f043f463f62,
0xbf04bf2c3f553f35,0x3edb3f18bf62bf46,0xbe16beac3f7b3f6d,0x3d493e79bf7fbf75,0xbf78bf803e488000,0x3f713f7dbe95bdc9,0xbf4ebf673f0e3ec4,0x3f3e3f5cbf22bef1,
0x3f093e893f623f7b,0xbf27becfbf4ebf71,0xbcc9bea13f7f3f6d,0xbdfb3e2fbf80bf78,0xbf13bf4a3f463f0e,0x3ee63f31bf5cbf2c,0xbf6fbf7f3e950000,0x3f5f3f7abedbbe16,
0x3f583f77bef1be48,0xbf42bf6a3f183eac,0x3f803f733dc93ec4,0xbf7ebf7c3d49be79,0x3f513f1d3f223f55,0xbf65bf39bf04bf3e,0x3eb83d973f753f80,0xbefcbe60bf67bf7d,
0x3ef13dc93f6d3f80,0xbf22be95bf55bf7b,0x3f753f463ec43f35,0xbf7fbf62be48bf0e,0x3f623f7fbec40000,0xbf46bf753f0e3e48,0x3e953f22bf6dbf35,0xbdc9bef13f7b3f55,
0x3f623f7fbec48000,0xbf46bf753f0e3e48,0x3e953f22bf6dbf35,0xbdc9bef13f7b3f55,0xbef1bdc9bf6dbf80,0x3f223e953f553f7b,0xbf75bf46bec4bf35,0x3f7f3f623e483f0e,
0xbcc93ee6bf7fbf55,0x3e89be603f7d3f71,0x3f513f7ebef10000,0xbf27bf6f3f2c3e79,0xbf6abf7f3e95be48,0x3f4a3f7cbf04bd49,0xbf58befcbf22bf6d,0x3f733f313edb3f4e,
0xbf80bf65bdc9bf0e,0x3f773f7abe163eac,0xbf13bdfbbf62bf80,0x3f423eb83f3e3f78,0x3ecfbd973f753f7b,0xbf1dbe2fbf5cbf80,0xbf09bf5f3f463ec4,0x3ea13f39bf67bf18,
0xbd49bf183f7b3f35,0xbe793eacbf7fbf62,0x3f673f043f0e3f6d,0xbf7dbf3ebe95bf46,0xbf2cbe16bf55bf80,0x3f5c3edb3f223f75,0xbf71bf783e48bec4,0x3f4e3f80bef13dc9,
0x3f803f4e3e483f35,0xbf78bf713dc9bef1,0x3edb3f5cbf55bec4,0xbe16bf2c3f753f22,0xbf3ebf7d3f0e8000,0x3f043f67bf46be95,0x3eacbe793f7b3f6d,0xbf18bd49bf62bf7f,
0xbe893ecfbf7fbf55,0x3f13bd973f673f78,0x3f653f7abe953ec4,0xbf31bf7e3f18bd49,0x3f1dbcc93f623f7b,0xbf58bea1bf2cbf7d,0xbf27bf7c3f220000,0x3eb83f5fbf5cbeac,
0xbf77bf6a3dc9bf0e,0x3f513f7fbedb3e79,0xbee63e60bf75bf6d,0x3f393dfb3f4e3f80,0x3f4a3f80bef13e48,0xbf09bf733f3e3e16,0x3f423e2f3f463f80,0xbf6fbefcbf04bf71,
0x3f553e483f353f80,0xbf7bbf0ebec4bf6d,0x3f0e3f7bbf350000,0xbe48bf553f6d3ec4,0xbf55be48bf35bf80,0x3f7b3f0e3ec43f6d,0xbf0ebf7b3f350000,0x3e483f55bf6dbec4,
0x3f0e3f7bbf358000,0xbe48bf553f6d3ec4,0xbf55be48bf35bf80,0x3f7b3f0e3ec43f6d,0xbf0ebf7b3f358000,0x3e483f55bf6dbec4,0x3f553e483f353f80,0xbf7bbf0ebec4bf6d,
0xbf77becfbef1bf7b,0x3f7c3f423d493f4e,0x3ee63f7abf460000,0xbcc9bf4a3f783edb,0x3f7e3f393dc93f55,0xbf58bf733eacbf04,0xbd97bf513f753ec4,0xbeb83efcbf7dbf3e,
0xbe89bf6a3f623e48,0xbe2f3f27bf80bf18,0xbf65be60bf22bf80,0x3f803f1d3e793f67,0xbdfb3f31bf7fbf0e,0x3f09bea13f713f5c,0x3f7f3f133e953f6d,0xbf6fbf5f3e16bf2c,
0x3f673f5cbe483f35,0xbf18bf803f22be95,0xbf3e3e16bf55bf6d,0x3f783eac3ef13f7f,0xbf71be79bf0ebf80,0x3f7d3f2c3dc93f62,0x3d49bf4e3f7b3ec4,0xbf043edbbf75bf46,
0xbedb3f04bf7bbf35,0x3f4ebd493f463f75,0xbf2cbf7d3f0ebec4,0x3e793f71bf62bdc9,0xbeacbf783f558000,0xbe163f3ebf7fbef1,0x3f803f183e483f6d,0xbf5cbf673e95bf22,
0xbcc9bf653f753e48,0xbefc3f09bf78bf2c,0xbf513dfbbf46bf6d,0x3f7f3ecf3eac3f7d,0x3f6f3f42bdc93f55,0xbf1dbf7c3f18bedb,0xbe60bf773f620000,0xbea13f31bf80bf04,
0x3f803ee63e953f7b,0xbf5fbf583e79bf3e,0xbf13bf7e3f22bec4,0x3d973f6abf71be16,0xbeb83f27bf7fbf0e,0x3f4abe2f3f4e3f67,0x3f7a3e893ef13f80,0xbf73bf393d49bf5c,
0x3f7f3e953ec43f80,0xbf62bf463e48bf55,0xbf223ef1bf6dbf35,0x3f753dc93f0e3f7b,0xbdc9bf753f6d0000,0xbef13f22bf7bbf0e,0x3f463f62bec43f35,0xbe95bf7f3f55be48,
0x3dc93f75bf6d8000,0x3ef1bf223f7b3f0e,0xbf46bf623ec4bf35,0x3e953f7fbf553e48,0x3f7f3e953ec43f80,0xbf62bf463e48bf55,0xbf223ef1bf6dbf35,0x3f753dc93f0e3f7b,
0xbf09bf773f22bf0e,0xbd973f6fbf78bd49,0xbcc93f73bf750000,0x3f1dbf133f713f18,0xbf7cbdfbbef1bf7b,0x3f653f31be163f67,0x3f6a3f27bdc93f6d,0xbefcbf7a3f2cbf04,
0x3f58be893f463f55,0xbf7fbeb8be79bf80,0xbf80bea1be95bf80,0x3f4a3f51beac3f4e,0xbe2fbf7e3f62be48,0xbee63f39bf7dbedb,0xbecf3f42bf7fbec4,0x3f5fbe603f3e3f5c,
0xbf4e3edbbf55bf35,0x3f803e793e953f7f,0x3f04bf3e3f7b3ec4,0xbf713e16bf22bf62,0xbf7dbeacbe48bf80,0x3f2c3f5cbef13f46,0x3f78bd493f0e3f6d,0xbf67bf183dc9bf75,
0xbf18bf673f0ebf35,0xbd493f78bf753dc9,0x3f5c3f2cbe483f6d,0xbeacbf7d3f46bef1,0x3e16bf713f7b8000,0xbf3e3f04bf62bf22,0x3e793f80bf553ec4,0x3edbbf4e3f7f3e95,
0x3ea13f7abf463f0e,0x3ecfbf5f3f803e16,0xbdfbbf803f62bec4,0xbf133f42bf78beac,0xbd973f7cbf753e48,0x3f39bf1d3f673f04,0x3e89bf6f3f7f0000,0xbf583ee6bf4ebf2c,
0xbf733e60bf22bf55,0x3f6a3efcbd493f7d,0x3f7ebcc93ef13f6d,0xbf51bf273e79bf71,0xbf7fbe2fbe95bf7b,0x3f313f4abedb3f5c,0x3f773eb83dc93f80,0xbf09bf653f18bf3e,
0x3f6d3ec400003f80,0xbec4bf6d3f35bf35,0xbf6dbec40000bf80,0x3ec43f6dbf353f35,0x3f6d3ec400003f80,0xbec4bf6d3f35bf35,0xbf6dbec40000bf80,0x3ec43f6dbf353f35,
0xbec43f6dbf808000,0x3f6dbec43f353f35,0x3ec4bf6d3f808000,0xbf6d3ec4bf35bf35,0xbec43f6dbf808000,0x3f6dbec43f353f35,0x3ec4bf6d3f808000,0xbf6d3ec4bf35bf35,
0x3f27bf513f753e48,0xbf803dfbbedbbf5c,0xbefc3f6abf7f0000,0x3f7abea13f183f3e,0x3f65bf093f463f0e,0xbf6fbe89bd49bf7d,0xbf4a3f31bf62bec4,0x3f7c3d973e793f71,
0x3f423f13be953f7b,0xbcc9bf7e3f67bf04,0xbf5fbecf3dc9bf80,0x3e603f73bf4e3f2c,0x3ee63f58bf223f55,0x3eb8bf773f80be16,0xbf1dbf393ef1bf6d,0xbe2f3f7fbf783eac,
0xbe16bf713f55bf35,0xbf2c3f5cbf75bdc9,0xbe793f80bf7b3ec4,0x3f67bf183f463ef1,0xbf4ebedb3e48bf80,0x3d493f78bf623f22,0x3f043f3ebf0e3f6d,0x3eacbf7d3f7fbe95,
0x3f7dbeac3f0e3f35,0xbf3ebf043e95bf7f,0xbf78bd49be48bf6d,0x3edb3f4ebf223f62,0x3f18bf673f7b8000,0xbf803e79bef1bf46,0xbf5c3f2cbf55bec4,0x3f713e163dc93f75,
0xbf13bf1d3ef1bf7b,0xbea13f80bf7d3edb,0x3f6f3d973dc93f6d,0xbe89bf583f3ebf5c,0xbf7a3efcbf22bf0e,0x3f423ecfbe793f80,0x3f31bf653f750000,0xbf7e3e2fbeacbf4e,
0x3f51bf4a3f623e48,0xbf73bcc9be16bf67,0xbeb83f7fbf7f3ec4,0x3f77bf093f2c3f04,0xbe60bf5f3f46bf55,0xbf273f6abf783d49,0x3f393ee6be953f80,0x3dfbbf7c3f71bf18,
0x3f223ef1bec43f80,0x3e95bf7f3f7bbf0e,0x3dc9bf753f6dbf35,0xbf623f46bf55be48,0xbf463f62bf6d0000,0x3f75bdc93e483f55,0x3f7fbe953ec43f35,0xbef1bf223f0ebf7b,
0xbf463f62bf6d8000,0x3f75bdc93e483f55,0x3f7fbe953ec43f35,0xbef1bf223f0ebf7b,0xbf22bef13ec4bf80,0xbe953f7fbf7b3f0e,0xbdc93f75bf6d3f35,0x3f62bf463f553e48,
0x3f6abd973dc93f55,0xbdfbbf513f4ebf67,0xbf583f5fbf620000,0x3f65bcc93d493f5c,0xbf393f73bf753e48,0x3f77be603e793f3e,0xbe2fbf4a3f46bf6d,0xbf423f6fbf713e16,
0xbecf3f7fbf7f3f0e,0x3f7ebf133f183edb,0xbf09befc3ef1bf80,0xbee63f80bf803f04,0xbf31bea13e95bf7b,0xbe893f7abf783f2c,0x3f7cbf1d3f223ec4,0xbf27beb83eacbf7d,
0x3f71be793e483f35,0xbe16bf3e3f46bf75,0xbd49bf4e3f55bf6d,0xbf5c3f67bf623dc9,0xbedbbf043f0ebf80,0xbf183f80bf7f3ef1,0xbf2c3f7dbf7b3ec4,0x3f78beac3e953f22,
0xbeac3f78bf7b3f35,0x3f7dbf2c3f223e95,0x3f80bf183f0e3ec4,0xbf04bedb3ef1bf7f,0x3f67bf5c3f558000,0xbf4ebd493dc9bf62,0xbf3ebe163e48bf6d,0xbe793f71bf753f46,
0x3f4abcc9bdc93f55,0x3e60bf653f71bf5c,0xbf423f7cbf753ec4,0x3f6abe893e163f2c,0xbefcbeb83ef1bf7b,0xbf133f7fbf803f18,0x3f73bf583f460000,0xbf31bdfb3e79bf67,
0xbf1d3f80bf7f3f0e,0x3f7abee63eac3f04,0xbf27be2f3e95bf6d,0xbecf3f77bf7d3f3e,0x3f5fbf6f3f62be48,0xbf513d973d49bf4e,0x3ea13f09bf223f80,0x3f39bf7e3f78bedb,
0x3e483f0ebf353f80,0x3f55bf7b3f6dbec4,0x3f7bbf553f350000,0xbf0ebe483ec4bf6d,0xbe48bf0e3f35bf80,0xbf553f7bbf6d3ec4,0xbf7b3f55bf350000,0x3f0e3e48bec43f6d,
0xbf7b3f55bf358000,0x3f0e3e48bec43f6d,0x3e483f0ebf353f80,0x3f55bf7b3f6dbec4,0x3f7bbf553f358000,0xbf0ebe483ec4bf6d,0xbe48bf0e3f35bf80,0xbf553f7bbf6d3ec4,
0xbdfb3f39bf623f7b,0x3f7abf653f3ebe16,0xbf7f3f51bf220000,0x3ecf3e89bf043f71,0x3efcbf6f3f7fbf55,0xbf7c3f27bedbbe79,0x3f73bf093e953ec4,0xbcc9bf1d3f4ebf80,
0xbf7e3f31bef1be48,0x3e603ee6bf2c3f7d,0xbd97bf133f46bf80,0xbf6a3f77bf5c3eac,0x3f5fbeb83dc93f0e,0x3e2fbf423f67bf78,0xbea13f58bf753f6d,0x3f80bf4a3f183d49,
0xbf3e3f7dbf7b3f35,0x3f5cbedb3dc93ef1,0x3eac3e79bf0e3f6d,0x3f4ebf803f75bf22,0x3d49bf183f55bf80,0xbf783f71bf463e95,0xbf673f04be48bec4,0xbe163f2cbf623f7f,
0xbf2c3e163e48bf35,0xbf043f67bf7f3f62,0xbf713f78bf553ec4,0x3f18bd49be953f46,0x3f80bf4e3f0e8000,0xbe79beac3f22bf75,0x3edbbf5c3f7bbf6d,0xbf7d3f3ebef1bdc9,
0xbf6f3f27be95be48,0xbdfb3f13bf5c3f80,0xbe60be893f22bf6d,0xbf653f80bf673f18,0x3f31bf733f7fbf55,0xbf5f3f09be16beac,0x3f7cbf4a3ef10000,0xbd97becf3f3ebf78,
0x3eb8bf423f75bf7b,0xbf7e3f51bf043d49,0x3f7abf773f46bec4,0xbee6bcc93edbbf4e,0x3f39bea1bdc93f0e,0x3efcbf583f7dbf71,0xbe2f3f1dbf623f80,0x3f7fbf6a3f2cbe79,
0xbe953f22bf6d3f80,0x3f7fbf623f0ebe48,0x3ef1bdc9bec43f35,0x3f46bf753f7bbf55,0x3f75bf463ec40000,0x3dc9bef13f55bf7b,0x3f62bf7f3f6dbf35,0xbf223e953e48bf0e,
0xbf753f46bec48000,0xbdc93ef1bf553f7b,0xbf623f7fbf6d3f35,0x3f22be95be483f0e,0xbe953f22bf6d3f80,0x3f7fbf623f0ebe48,0x3ef1bdc9bec43f35,0x3f46bf753f7bbf55,
0xbf7c3f7ebf463f0e,0x3ea1bcc9bf043f3e,0xbf6a3f42be950000,0xbe893f09bf673f7d,0xbe603efcbf623f7b,0x3f7fbf6f3f18beac,0xbf393f65bf7f3f6d,0x3f4abf133d493e79,
0xbe2fbdfb3f22bf55,0xbf733f80bf5c3f2c,0x3ecfbf273f75bf80,0xbf773f58bedb3e16,0xbf7a3f5fbef13e48,0xbd973eb8bf4e3f71,0xbf313ee63dc9bec4,0xbf1d3f51bf803f78,
0xbe793d493f0ebf35,0xbf713f7dbf623f46,0xbf183edb3e48bec4,0xbf3e3f5cbf7f3f75,0x3f04bf2c3f7bbf80,0xbf673f4ebe953dc9,0x3e16beac3f55bf6d,0xbf803f78bf223ef1,
0x3f78bf803f55bf35,0xbeac3e163ef1bf22,0x3f4ebf673f7bbf6d,0xbf2c3f043dc9be95,0x3f5cbf3e3e488000,0x3edbbf183f75bf7f,0x3f7dbf713f0ebec4,0x3d49be793f46bf62,
0x3f7fbf7c3f22bf0e,0x3cc9bdfb3f3ebf4e,0x3f77bf6f3ef1bec4,0x3e60bea13f5cbf67,0x3f65bf583e95be48,0x3ecfbefc3f71bf78,0x3f4abf393dc90000,0x3f13bf273f7dbf80,
0xbd973e2fbf463f55,0x3f80bf7e3f2cbf18,0xbe893eb8bf623f6d,0x3f7abf733f04bedb,0xbee63f09bf753f7b,0x3f6abf5f3eacbe79,0xbf1d3f31bf7f3f80,0x3f51bf423e16bd49,
0x3f35bf35bf803f80,0xbf353f3500000000,0x3f35bf35bf803f80,0xbf353f3500000000,0x3f35bf35bf803f80,0xbf353f3500000000,0x3f35bf35bf803f80,0xbf353f3500000000,
0x3f35bf3580008000,0x3f35bf35bf803f80,0x3f35bf3580008000,0x3f35bf35bf803f80,0x3f35bf3580008000,0x3f35bf35bf803f80,0x3f35bf3580008000,0x3f35bf35bf803f80,
0x3ee63f09bf62bf55,0xbecfbefc3f673f5c,0x3f1d3f31bf46bf35,0xbf13bf273f4e3f3e,0x3d973e2fbf7fbf7b,0xbcc9bdfb3f803f7d,0x3e893eb8bf75bf6d,0xbe60bea13f783f71,
0xbf65bf58bef1bf0e,0x3f6a3f5f3edb3f04,0xbf4abf39bf22bf35,0x3f513f423f183f2c,0xbf7fbf7cbdc9be48,0x3f803f7e3d493e16,0xbf77bf6fbe95bec4,0x3f7a3f733e793eac,
0xbf04bf2c3f553f35,0x3edb3f18bf62bf46,0xbe16beac3f7b3f6d,0x3d493e79bf7fbf75,0xbf78bf803e480000,0x3f713f7dbe95bdc9,0xbf4ebf673f0e3ec4,0x3f3e3f5cbf22bef1,
0x3f5c3f3e3f0e3f35,0xbf67bf4ebef1bf22,0x3f7d3f713e483ec4,0xbf80bf78bdc9be95,0x3e793d493f7b3f80,0xbeacbe16bf75bf7f,0x3f183edb3f553f6d,0xbf2cbf04bf46bf62,
0x3e603efcbf75bf55,0xbd97beb83f7d3f67,0x3f393f65bf22bec4,0xbf1dbf513f3e3f04,0x3f7c3f7ebdc93e48,0xbf73bf803e79bd49,0x3f6a3f423ef13f35,0xbf77bf58beacbf18,
0xbf7abf5fbe95bf0e,0x3f7f3f6f3e163edb,0xbf31bee6bf46bf6d,0x3f4a3f133f2c3f5c,0xbe2f3dfbbf7fbf7b,0x3ea13cc93f783f80,0x3ecf3f27bf62bf35,0xbe89bf093f713f4e,
0xbef1bdc9bf6dbf80,0x3f223e953f553f7b,0xbf75bf46bec4bf35,0x3f7f3f623e483f0e,0xbf62bf7f3ec40000,0x3f463f75bf0ebe48,0xbe95bf223f6d3f35,0x3dc93ef1bf7bbf55,
0xbf62bf7f3ec48000,0x3f463f75bf0ebe48,0xbe95bf223f6d3f35,0x3dc93ef1bf7bbf55,0x3ef13dc93f6d3f80,0xbf22be95bf55bf7b,0x3f753f463ec43f35,0xbf7fbf62be48bf0e,
0x3f393ea13f463f7b,0xbf5fbf09bf18bf67,0xbe2fbf1d3f753f35,0xbd973ecfbf80bf5c,0x3eb83f42bf62bf0e,0xbdfbbf133f783f3e,0x3f7a3f77bdc93ec4,0xbf65bf803eacbe16,
0x3f313f73bf22be48,0xbefcbf583f4e3edb,0x3f7c3f4a3e953f35,0xbf7fbf6abd49bf04,0xbf6fbf27bef1bf55,0x3f7e3f513e793f2c,0xbe603e89bf7fbf6d,0x3ee6bcc93f713f7d,
0xbf80bf4ebe48bf35,0x3f783f71bdc93ef1,0xbedbbf5c3f553ec4,0x3e163f2cbf75bf22,0x3f3e3f7dbf0e0000,0xbf04bf673f463e95,0xbeac3e79bf7bbf6d,0x3f183d493f623f7f,
0xbd49bf183f7b3f35,0xbe793eacbf7fbf62,0x3f673f043f0e3f6d,0xbf7dbf3ebe95bf46,0xbf2cbe16bf55bf80,0x3f5c3edb3f223f75,0xbf71bf783e48bec4,0x3f4e3f80bef13dc9,
0x3efc3f6fbf46be48,0xbe2fbf423f713f04,0x3f733f093ef13f6d,0xbf80bf4abe16bf3e,0xbdfbbf393f753f0e,0xbe603ee6bf80bf4e,0xbf7fbf51bdc9bf35,0x3f6a3f77be793edb,
0xbf5fbeb8bf22bf7b,0x3f7c3f273eac3f5c,0x3ea13f58bf62bec4,0x3cc9bf1d3f7d3f2c,0x3f7e3f313e953f55,0xbf7abf653d49bf18,0x3d97bf133f7f3f35,0xbecf3e89bf78bf67,
0x3f553e483f353f80,0xbf7bbf0ebec4bf6d,0x3f0e3f7bbf350000,0xbe48bf553f6d3ec4,0xbf55be48bf35bf80,0x3f7b3f0e3ec43f6d,0xbf0ebf7b3f350000,0x3e483f55bf6dbec4,
0x3f0e3f7bbf358000,0xbe48bf553f6d3ec4,0xbf55be48bf35bf80,0x3f7b3f0e3ec43f6d,0xbf0ebf7b3f358000,0x3e483f55bf6dbec4,0x3f553e483f353f80,0xbf7bbf0ebec4bf6d,
0xbf5fbf6f3e95bf0e,0x3f133f7fbf2c3e16,0xbea13f09bf7fbf35,0x3f31bdfb3f5c3f71,0x3f1d3f80bf223e48,0xbe60bf653f673e79,0x3f27be2f3f623f6d,0xbf6abe89bf18bf80,
0x3efcbeb83f753f55,0xbf51bd97bf3ebf7d,0xbf73bf583dc9bf35,0x3f393f7ebf043eac,0xbf4abcc9bf46bf7b,0x3f7a3ee63edb3f78,0x3f423f7cbef13ec4,0xbecfbf773f4e3d49,
0xbedb3f04bf7bbf35,0x3f4ebd493f463f75,0xbf2cbf7d3f0ebec4,0x3e793f71bf62bdc9,0xbeacbf783f550000,0xbe163f3ebf7fbef1,0x3f803f183e483f6d,0xbf5cbf673e95bf22,
0xbf67bf5c3e48bf35,0x3f183f80bf223e95,0x3f3ebe163f553f6d,0xbf78beacbef1bf7f,0x3f713e793f0e3f80,0xbf7dbf2cbdc9bf62,0xbd493f4ebf7bbec4,0x3f04bedb3f753f46,
0x3f393f73bef13f0e,0xbe89bf7a3f5cbd49,0x3e2fbf4a3f7f3ec4,0xbf273eb8bf67bf4e,0xbf6abd97bf22bf7b,0x3f7e3f133e163f71,0x3f583f5fbe953f35,0xbee6bf803f3ebe79,
0xbf313ea1bf62bf55,0x3f773e603f043f80,0x3f7c3f1d3dc93f6d,0xbf42bf6f3edbbf18,0xbecfbf7f3f46be48,0xbdfb3f51bf7dbeac,0xbf093efcbf75bf35,0x3f653cc93f2c3f78,
0xbf7fbe95bec4bf80,0x3f623f46be483f55,0x3f22bef13f6d3f35,0xbf75bdc9bf0ebf7b,0x3dc93f75bf6d0000,0x3ef1bf223f7b3f0e,0xbf46bf623ec4bf35,0x3e953f7fbf553e48,
0xbdc9bf753f6d8000,0xbef13f22bf7bbf0e,0x3f463f62bec43f35,0xbe95bf7f3f55be48,0xbf7fbe95bec4bf80,0x3f623f46be483f55,0x3f22bef13f6d3f35,0xbf75bdc9bf0ebf7b,
0xbe603f5fbf7fbe48,0x3f42becf3f5c3f3e,0x3f39bee63f623f35,0xbf7ebe2fbedbbf7d,0x3f513f4abe953f55,0xbea1bf803f4ebeac,0xbeb8bf7f3f46bec4,0xbe893f58bf80be79,
0xbf7abefcbdc9bf7b,0x3f273f6abf043f2c,0x3f313f65bef13f35,0xbdfbbf7c3f67be16,0xbf133f1dbf75bf0e,0x3f73bcc93f183f71,0x3f6fbd973f223f6d,0xbf77bf09bd49bf78,
0x3f183f67bf0e3f35,0x3d49bf783f75bdc9,0xbf5cbf2c3e48bf6d,0x3eac3f7dbf463ef1,0xbe163f71bf7b0000,0x3f3ebf043f623f22,0xbe79bf803f55bec4,0xbedb3f4ebf7fbe95,
0xbf4e3edbbf55bf35,0x3f803e793e953f7f,0x3f04bf3e3f7b3ec4,0xbf713e16bf22bf62,0xbf7dbeacbe48bf80,0x3f2c3f5cbef13f46,0x3f78bd493f0e3f6d,0xbf67bf183dc9bf75,
0x3f653f09bdc93f7b,0xbeb8bf773f3ebf18,0xbf4abf313e95bf6d,0x3e2f3f7fbf5c3edb,0x3f273f51bef13f55,0x3cc9bf7e3f71be79,0xbefcbf6a3f22bf35,0xbe603f73bf7d3d49,
0xbee63f58bf7fbe48,0x3f6fbe893f2c3f4e,0x3f1dbf393f753ec4,0xbf7c3d97bf04bf67,0xbf423f13bf62bf0e,0x3f803dfb3eac3f78,0x3f5fbecf3f463f35,0xbf7abea1be16bf80,
0x3f6d3ec400003f80,0xbec4bf6d3f35bf35,0xbf6dbec40000bf80,0x3ec43f6dbf353f35,0x3f6d3ec400003f80,0xbec4bf6d3f35bf35,0xbf6dbec40000bf80,0x3ec43f6dbf353f35,
0xbec43f6dbf808000,0x3f6dbec43f353f35,0x3ec4bf6d3f808000,0xbf6d3ec4bf35bf35,0xbec43f6dbf808000,0x3f6dbec43f353f35,0x3ec4bf6d3f808000,0xbf6d3ec4bf35bf35,
0x3f7fbe2f3ef13f55,0xbf39bf1d3eacbf78,0xbf773eb8bf22bf35,0x3f583ee6be163f80,0x3f733e603dc93f7b,0xbecfbf5f3f2cbf4e,0xbf7ebcc9be95bf6d,0x3f133f42bf043f67,
0x3d973f7cbf623f0e,0x3f31bf4a3f713e79,0xbe89bf6f3f46bf35,0xbf093f65bf7dbd49,0xbea13f7abf7f3e48,0x3f6abefc3f3e3f18,0x3dfbbf803f75bec4,0xbf513f27bf5cbedb,
0x3f7dbeac3f0e3f35,0xbf3ebf043e95bf7f,0xbf78bd49be48bf6d,0x3edb3f4ebf223f62,0x3f18bf673f7b0000,0xbf803e79bef1bf46,0xbf5c3f2cbf55bec4,0x3f713e163dc93f75,
0x3e163f71bf553f35,0x3f2cbf5c3f753dc9,0x3e79bf803f7bbec4,0xbf673f18bf46bef1,0x3f4e3edbbe483f80,0xbd49bf783f62bf22,0xbf04bf3e3f0ebf6d,0xbeac3f7dbf7f3e95,
0x3f7cbdfb3e953f55,0xbee6bf393f18bf71,0xbf6a3f27bf46bec4,0x3f5f3e60bd493f78,0x3f09bf773f7fbe48,0xbf7f3eb8bf04bf2c,0x3cc93f73bf623f35,0x3f4abf513f673e16,
0xbe2f3f7ebf753f0e,0x3f65bf313f4e3eac,0xbecfbf423f22bf6d,0xbefc3f7abf803e79,0x3f583e89bdc93f7b,0xbd97bf6f3f5cbf3e,0xbf803ea1bef1bf35,0x3f1d3f13bedb3f7d,
0xbf22bef13ec4bf80,0xbe953f7fbf7b3f0e,0xbdc93f75bf6d3f35,0x3f62bf463f553e48,0x3f46bf623f6d0000,0xbf753dc9be48bf55,0xbf7f3e95bec4bf35,0x3ef13f22bf0e3f7b,
0x3f46bf623f6d8000,0xbf753dc9be48bf55,0xbf7f3e95bec4bf35,0x3ef13f22bf0e3f7b,0x3f223ef1bec43f80,0x3e95bf7f3f7bbf0e,0x3dc9bf753f6dbf35,0xbf623f46bf55be48,
0xbeb8bf273f22bf7b,0xbf1d3f7cbf7d3eac,0x3f7abe893e953f35,0xbea1bf313f2cbf78,0x3f80bee63ef13f0e,0xbefcbf093f04bf80,0xbf133f7ebf7f3ec4,0x3f7fbecf3edb3f18,
0x3f6fbf423f463e48,0xbf4abe2f3e16bf71,0xbe603f77bf753f35,0x3f73bf393f3e3e79,0xbcc93f65bf623f55,0x3f5fbf583f5c3d49,0xbf51bdfb3dc9bf6d,0xbd973f6abf673f4e,
0x3eacbf783f7bbf35,0xbf7d3f2cbf22be95,0xbf803f18bf0ebec4,0x3f043edbbef13f7f,0xbf673f5cbf550000,0x3f4e3d49bdc93f62,0x3f3e3e16be483f6d,0x3e79bf713f75bf46,
0x3f71be793e483f35,0xbe16bf3e3f46bf75,0xbd49bf4e3f55bf6d,0xbf5c3f67bf623dc9,0xbedbbf043f0ebf80,0xbf183f80bf7f3ef1,0xbf2c3f7dbf7b3ec4,0x3f78beac3e953f22,
0x3f7ebf393f223e48,0xbf09bea13edbbf78,0xbd973f51bf623f6d,0x3f6fbf5f3f4ebd49,0xbf773ecfbe95bf0e,0x3e2f3f27bf3e3f7d,0x3ee6bf7a3f7fbf35,0xbf803f1dbf04beac,
0x3dfb3f31bf463f7b,0x3f58bf733f67be79,0xbf7f3f13bef1bec4,0x3eb83efcbf183f80,0x3e89bf6a3f75bf55,0xbf7c3f42bf2cbe16,0x3f65be603dc93f35,0x3cc9bf4a3f5cbf71,
0x3e483f0ebf353f80,0x3f55bf7b3f6dbec4,0x3f7bbf553f350000,0xbf0ebe483ec4bf6d,0xbe48bf0e3f35bf80,0xbf553f7bbf6d3ec4,0xbf7b3f55bf350000,0x3f0e3e48bec43f6d,
0xbf7b3f55bf358000,0x3f0e3e48bec43f6d,0x3e483f0ebf353f80,0x3f55bf7b3f6dbec4,0x3f7bbf553f358000,0xbf0ebe483ec4bf6d,0xbe48bf0e3f35bf80,0xbf553f7bbf6d3ec4,
0xbf4a3f80bf753f0e,0x3f58bea13d493f18,0xbf423e2f3dc9bf35,0xbeb83f5fbf783f67,0x3f77bf6a3f46be48,0xbf13bd973eacbf5c,0x3ee63e60bef13f6d,0x3f31bf7e3f7dbf2c,
0xbf1dbcc93e95bf55,0xbf093f73bf803f4e,0x3f27bf7c3f7fbf35,0xbf6f3efcbe79bedb,0x3e893ecfbf223f7b,0x3f51bf7f3f71bf04,0xbf653f7abf623ec4,0x3f39bdfbbe163f3e,
0xbf2c3e163e48bf35,0xbf043f67bf7f3f62,0xbf713f78bf553ec4,0x3f18bd49be953f46,0x3f80bf4e3f0e0000,0xbe79beac3f22bf75,0x3edbbf5c3f7bbf6d,0xbf7d3f3ebef1bdc9,
0x3f3ebf7d3f7bbf35,0xbf5c3edbbdc9bef1,0xbeacbe793f0ebf6d,0xbf4e3f80bf753f22,0xbd493f18bf553f80,0x3f78bf713f46be95,0x3f67bf043e483ec4,0x3e16bf2c3f62bf7f,
0x3f6abf7f3f62bf0e,0xbf1d3e2f3e79bf2c,0x3f58befc3dc93ec4,0x3ea1bf393f71bf7d,0x3cc93ee6bf463f7b,0x3f77bf7a3f4ebedb,0xbf513f7ebf753f35,0x3f42beb8bd493f04,
0x3ecf3d97bef13f55,0x3f4abf7c3f78bf3e,0xbf093f5fbf7f3f6d,0x3f73bf313eac3e16,0xbf803f65bf223e48,0x3e893e60bf183f67,0xbf133dfb3e95bf35,0xbf273f6fbf803f5c,
0x3e95bf223f6dbf80,0xbf7f3f62bf0e3e48,0xbef13dc93ec4bf35,0xbf463f75bf7b3f55,0xbf753f46bec40000,0xbdc93ef1bf553f7b,0xbf623f7fbf6d3f35,0x3f22be95be483f0e,
0x3f75bf463ec48000,0x3dc9bef13f55bf7b,0x3f62bf7f3f6dbf35,0xbf223e953e48bf0e,0x3e95bf223f6dbf80,0xbf7f3f62bf0e3e48,0xbef13dc93ec4bf35,0xbf463f75bf7b3f55,
0x3f51bf1d3dc93e48,0x3ee6bf313f78bf80,0x3eb8bd97bef13f35,0x3f5fbf7a3f71bf4e,0x3f58bf773f75bf55,0xbf273ecf3e16bedb,0x3f80bf733f22bec4,0xbdfbbe2f3f2cbf5c,
0xbf133f4abf7f3f7b,0x3f65bf393e793d49,0xbf6f3f7fbf623f35,0x3efcbe60beac3f18,0x3f09be89be953f0e,0x3f42bf6a3f7dbf67,0xbcc93ea1bf463f6d,0x3f7ebf7c3f3ebf04,
0xbf783f80bf553f35,0x3eacbe16bef13f22,0xbf4e3f67bf7b3f6d,0x3f2cbf04bdc93e95,0xbf5c3f3ebe480000,0xbedb3f18bf753f7f,0xbf7d3f71bf0e3ec4,0xbd493e79bf463f62,
0xbe793d493f0ebf35,0xbf713f7dbf623f46,0xbf183edb3e48bec4,0xbf3e3f5cbf7f3f75,0x3f04bf2c3f7bbf80,0xbf673f4ebe953dc9,0x3e16beac3f55bf6d,0xbf803f78bf223ef1,
0x3f42bf513f7fbf7b,0xbf313f1d3d49be16,0x3f5fbf6a3f75bf6d,0xbf093ee63e79beac,0x3f73bf7a3f62bf55,0xbeb83e893edbbf04,0x3f7ebf803f46bf35,0xbe2f3d973f18bf2c,
0x3f27bf13bdc93e48,0x3f39bf4a3f80bf7d,0x3efcbecfbe953ec4,0x3f58bf653f78bf71,0x3ea1be60bef13f0e,0x3f6fbf773f67bf5c,0x3dfbbcc9bf223f35,0x3f7cbf7f3f4ebf3e,
0x3f35bf35bf803f80,0xbf353f3500000000,0x3f35bf35bf803f80,0xbf353f3500000000,0x3f35bf35bf803f80,0xbf353f3500000000,0x3f35bf35bf803f80,0xbf353f3500000000,
0x3f35bf3580008000,0x3f35bf35bf803f80,0x3f35bf3580008000,0x3f35bf35bf803f80,0x3f35bf3580008000,0x3f35bf35bf803f80,0x3f35bf3580008000,0x3f35bf35bf803f80,
0xbea1be60bf75bf7b,0x3eb83e893f713f78,0xbdfbbcc9bf7fbf80,0x3e2f3d973f7d3f80,0xbf27bf13bf46bf55,0x3f313f1d3f3e3f4e,0xbefcbecfbf62bf6d,0x3f093ee63f5c3f67,
0xbf73bf7a3e953e48,0x3f6f3f77beacbe79,0xbf7ebf803dc98000,0x3f7c3f7fbe16bd49,0xbf42bf513f223f0e,0x3f393f4abf2cbf18,0xbf5fbf6a3ef13ec4,0x3f583f65bf04bedb,
0x3f5c3f3e3f0e3f35,0xbf67bf4ebef1bf22,0x3f7d3f713e483ec4,0xbf80bf78bdc9be95,0x3e793d493f7b3f80,0xbeacbe16bf75bf7f,0x3f183edb3f553f6d,0xbf2cbf04bf46bf62,
0x3f043f2cbf55bf35,0xbedbbf183f623f46,0x3e163eacbf7bbf6d,0xbd49be793f7f3f75,0x3f783f80be488000,0xbf71bf7d3e953dc9,0x3f4e3f67bf0ebec4,0xbf3ebf5c3f223ef1,
0xbf58bf773ef13e48,0x3f423f6abf18beac,0xbf80bf73bdc9bec4,0x3f7e3f7cbd493e79,0xbf51bf1dbf22bf55,0x3f653f393f043f3e,0xbeb8bd97bf75bf80,0x3efc3e603f673f7d,
0x3f093e893f623f7b,0xbf27becfbf4ebf71,0xbcc9bea13f7f3f6d,0xbdfb3e2fbf80bf78,0xbf13bf4a3f463f0e,0x3ee63f31bf5cbf2c,0xbf6fbf7f3e958000,0x3f5f3f7abedbbe16,
0x3ef13dc93f6d3f80,0xbf22be95bf55bf7b,0x3f753f463ec43f35,0xbf7fbf62be48bf0e,0x3f623f7fbec40000,0xbf46bf753f0e3e48,0x3e953f22bf6dbf35,0xbdc9bef13f7b3f55,
0x3f623f7fbec48000,0xbf46bf753f0e3e48,0x3e953f22bf6dbf35,0xbdc9bef13f7b3f55,0xbef1bdc9bf6dbf80,0x3f223e953f553f7b,0xbf75bf46bec4bf35,0x3f7f3f623e483f0e,
0xbf80bf65bdc9bf0e,0x3f773f7abe163eac,0xbf13bdfbbf62bf80,0x3f423eb83f3e3f78,0x3ecfbd973f753f7b,0xbf1dbe2fbf5cbf80,0xbf09bf5f3f463ec4,0x3ea13f39bf67bf18,
0x3cc9bee63f7f3f55,0xbe893e60bf7dbf71,0xbf51bf7e3ef18000,0x3f273f6fbf2cbe79,0x3f6a3f7fbe953e48,0xbf4abf7c3f043d49,0x3f583efc3f223f6d,0xbf73bf31bedbbf4e,
0x3d493f18bf7bbf35,0x3e79beac3f7f3f62,0xbf67bf04bf0ebf6d,0x3f7d3f3e3e953f46,0x3f2c3e163f553f80,0xbf5cbedbbf22bf75,0x3f713f78be483ec4,0xbf4ebf803ef1bdc9,
0xbf80bf4ebe48bf35,0x3f783f71bdc93ef1,0xbedbbf5c3f553ec4,0x3e163f2cbf75bf22,0x3f3e3f7dbf0e8000,0xbf04bf673f463e95,0xbeac3e79bf7bbf6d,0x3f183d493f623f7f,
0x3f773f6abdc93f0e,0xbf51bf7f3edbbe79,0x3ee6be603f753f6d,0xbf39bdfbbf4ebf80,0xbf4abf803ef1be48,0x3f093f73bf3ebe16,0xbf42be2fbf46bf80,0x3f6f3efc3f043f71,
0xbe893ecfbf7fbf55,0x3f13bd973f673f78,0x3f653f7abe953ec4,0xbf31bf7e3f18bd49,0x3f1dbcc93f623f7b,0xbf58bea1bf2cbf7d,0xbf27bf7c3f228000,0x3eb83f5fbf5cbeac,
0x3f553e483f353f80,0xbf7bbf0ebec4bf6d,0x3f0e3f7bbf350000,0xbe48bf553f6d3ec4,0xbf55be48bf35bf80,0x3f7b3f0e3ec43f6d,0xbf0ebf7b3f350000,0x3e483f55bf6dbec4,
0x3f0e3f7bbf358000,0xbe48bf553f6d3ec4,0xbf55be48bf35bf80,0x3f7b3f0e3ec43f6d,0xbf0ebf7b3f358000,0x3e483f55bf6dbec4,0x3f553e483f353f80,0xbf7bbf0ebec4bf6d,
0xbe89bf6a3f623e48,0xbe2f3f27bf80bf18,0xbf65be60bf22bf80,0x3f803f1d3e793f67,0xbdfb3f31bf7fbf0e,0x3f09bea13f713f5c,0x3f7f3f133e953f6d,0xbf6fbf5f3e16bf2c,
0x3f773ecf3ef13f7b,0xbf7cbf42bd49bf4e,0xbee6bf7a3f468000,0x3cc93f4abf78bedb,0xbf7ebf39bdc9bf55,0x3f583f73beac3f04,0x3d973f51bf75bec4,0x3eb8befc3f7d3f3e,
0xbf67bf5c3e48bf35,0x3f183f80bf223e95,0x3f3ebe163f553f6d,0xbf78beacbef1bf7f,0x3f713e793f0e3f80,0xbf7dbf2cbdc9bf62,0xbd493f4ebf7bbec4,0x3f04bedb3f753f46,
0x3edbbf043f7b3f35,0xbf4e3d49bf46bf75,0x3f2c3f7dbf0e3ec4,0xbe79bf713f623dc9,0x3eac3f78bf558000,0x3e16bf3e3f7f3ef1,0xbf80bf18be48bf6d,0x3f5c3f67be953f22,
0xbf80bee6be95bf7b,0x3f5f3f58be793f3e,0x3f133f7ebf223ec4,0xbd97bf6a3f713e16,0x3eb8bf273f7f3f0e,0xbf4a3e2fbf4ebf67,0xbf7abe89bef1bf80,0x3f733f39bd493f5c,
0xbcc9bf653f753e48,0xbefc3f09bf78bf2c,0xbf513dfbbf46bf6d,0x3f7f3ecf3eac3f7d,0x3f6f3f42bdc93f55,0xbf1dbf7c3f18bedb,0xbe60bf773f628000,0xbea13f31bf80bf04,
0x3f7f3e953ec43f80,0xbf62bf463e48bf55,0xbf223ef1bf6dbf35,0x3f753dc93f0e3f7b,0xbdc9bf753f6d0000,0xbef13f22bf7bbf0e,0x3f463f62bec43f35,0xbe95bf7f3f55be48,
0x3dc93f75bf6d8000,0x3ef1bf223f7b3f0e,0xbf46bf623ec4bf35,0x3e953f7fbf553e48,0x3f7f3e953ec43f80,0xbf62bf463e48bf55,0xbf223ef1bf6dbf35,0x3f753dc93f0e3f7b,
0x3f58be893f463f55,0xbf7fbeb8be79bf80,0xbf80bea1be95bf80,0x3f4a3f51beac3f4e,0xbe2fbf7e3f62be48,0xbee63f39bf7dbedb,0xbecf3f42bf7fbec4,0x3f5fbe603f3e3f5c,
0x3f093f77bf223f0e,0x3d97bf6f3f783d49,0x3cc9bf733f758000,0xbf1d3f13bf71bf18,0x3f7c3dfb3ef13f7b,0xbf65bf313e16bf67,0xbf6abf273dc9bf6d,0x3efc3f7abf2c3f04,
0x3f4ebedb3f553f35,0xbf80be79be95bf7f,0xbf043f3ebf7bbec4,0x3f71be163f223f62,0x3f7d3eac3e483f80,0xbf2cbf5c3ef1bf46,0xbf783d49bf0ebf6d,0x3f673f18bdc93f75,
0x3f183f67bf0e3f35,0x3d49bf783f75bdc9,0xbf5cbf2c3e48bf6d,0x3eac3f7dbf463ef1,0xbe163f71bf7b8000,0x3f3ebf043f623f22,0xbe79bf803f55bec4,0xbedb3f4ebf7fbe95,
0x3f73be603f223f55,0xbf6abefc3d49bf7d,0xbf7e3cc9bef1bf6d,0x3f513f27be793f71,0x3f7f3e2f3e953f7b,0xbf31bf4a3edbbf5c,0xbf77beb8bdc9bf80,0x3f093f65bf183f3e,
0x3ea13f7abf463f0e,0x3ecfbf5f3f803e16,0xbdfbbf803f62bec4,0xbf133f42bf78beac,0xbd973f7cbf753e48,0x3f39bf1d3f673f04,0x3e89bf6f3f7f8000,0xbf583ee6bf4ebf2c,
0x3f6d3ec400003f80,0xbec4bf6d3f35bf35,0xbf6dbec40000bf80,0x3ec43f6dbf353f35,0x3f6d3ec400003f80,0xbec4bf6d3f35bf35,0xbf6dbec40000bf80,0x3ec43f6dbf353f35,
0xbec43f6dbf808000,0x3f6dbec43f353f35,0x3ec4bf6d3f808000,0xbf6d3ec4bf35bf35,0xbec43f6dbf808000,0x3f6dbec43f353f35,0x3ec4bf6d3f808000,0xbf6d3ec4bf35bf35,
0x3f423f13be953f7b,0xbcc9bf7e3f67bf04,0xbf5fbecf3dc9bf80,0x3e603f73bf4e3f2c,0x3ee63f58bf223f55,0x3eb8bf773f80be16,0xbf1dbf393ef1bf6d,0xbe2f3f7fbf783eac,
0xbf273f51bf75be48,0x3f80bdfb3edb3f5c,0x3efcbf6a3f7f8000,0xbf7a3ea1bf18bf3e,0xbf653f09bf46bf0e,0x3f6f3e893d493f7d,0x3f4abf313f623ec4,0xbf7cbd97be79bf71,
0x3e163f71bf553f35,0x3f2cbf5c3f753dc9,0x3e79bf803f7bbec4,0xbf673f18bf46bef1,0x3f4e3edbbe483f80,0xbd49bf783f62bf22,0xbf04bf3e3f0ebf6d,0xbeac3f7dbf7f3e95,
0xbf7d3eacbf0ebf35,0x3f3e3f04be953f7f,0x3f783d493e483f6d,0xbedbbf4e3f22bf62,0xbf183f67bf7b8000,0x3f80be793ef13f46,0x3f5cbf2c3f553ec4,0xbf71be16bdc9bf75,
0xbf513f4abf62be48,0x3f733cc93e163f67,0x3eb8bf7f3f7fbec4,0xbf773f09bf2cbf04,0x3e603f5fbf463f55,0x3f27bf6a3f78bd49,0xbf39bee63e95bf80,0xbdfb3f7cbf713f18,
0xbf13bf1d3ef1bf7b,0xbea13f80bf7d3edb,0x3f6f3d973dc93f6d,0xbe89bf583f3ebf5c,0xbf7a3efcbf22bf0e,0x3f423ecfbe793f80,0x3f31bf653f758000,0xbf7e3e2fbeacbf4e,
0x3f223ef1bec43f80,0x3e95bf7f3f7bbf0e,0x3dc9bf753f6dbf35,0xbf623f46bf55be48,0xbf463f62bf6d0000,0x3f75bdc93e483f55,0x3f7fbe953ec43f35,0xbef1bf223f0ebf7b,
0xbf463f62bf6d8000,0x3f75bdc93e483f55,0x3f7fbe953ec43f35,0xbef1bf223f0ebf7b,0xbf22bef13ec4bf80,0xbe953f7fbf7b3f0e,0xbdc93f75bf6d3f35,0x3f62bf463f553e48,
0xbecf3f7fbf7f3f0e,0x3f7ebf133f183edb,0xbf09befc3ef1bf80,0xbee63f80bf803f04,0xbf31bea13e95bf7b,0xbe893f7abf783f2c,0x3f7cbf1d3f223ec4,0xbf27beb83eacbf7d,
0xbf6a3d97bdc9bf55,0x3dfb3f51bf4e3f67,0x3f58bf5f3f628000,0xbf653cc9bd49bf5c,0x3f39bf733f75be48,0xbf773e60be79bf3e,0x3e2f3f4abf463f6d,0x3f42bf6f3f71be16,
0xbf713e79be48bf35,0x3e163f3ebf463f75,0x3d493f4ebf553f6d,0x3f5cbf673f62bdc9,0x3edb3f04bf0e3f80,0x3f18bf803f7fbef1,0x3f2cbf7d3f7bbec4,0xbf783eacbe95bf22,
0x3eacbf783f7bbf35,0xbf7d3f2cbf22be95,0xbf803f18bf0ebec4,0x3f043edbbef13f7f,0xbf673f5cbf558000,0x3f4e3d49bdc93f62,0x3f3e3e16be483f6d,0x3e79bf713f75bf46,
0x3f1dbf803f7fbf0e,0xbf7a3ee6beacbf04,0x3f273e2fbe953f6d,0x3ecfbf773f7dbf3e,0xbf5f3f6fbf623e48,0x3f51bd97bd493f4e,0xbea1bf093f22bf80,0xbf393f7ebf783edb,
0x3f4abcc9bdc93f55,0x3e60bf653f71bf5c,0xbf423f7cbf753ec4,0x3f6abe893e163f2c,0xbefcbeb83ef1bf7b,0xbf133f7fbf803f18,0x3f73bf583f468000,0xbf31bdfb3e79bf67,
0x3e483f0ebf353f80,0x3f55bf7b3f6dbec4,0x3f7bbf553f350000,0xbf0ebe483ec4bf6d,0xbe48bf0e3f35bf80,0xbf553f7bbf6d3ec4,0xbf7b3f55bf350000,0x3f0e3e48bec43f6d,
0xbf7b3f55bf358000,0x3f0e3e48bec43f6d,0x3e483f0ebf353f80,0x3f55bf7b3f6dbec4,0x3f7bbf553f358000,0xbf0ebe483ec4bf6d,0xbe48bf0e3f35bf80,0xbf553f7bbf6d3ec4,
0xbf7e3f31bef1be48,0x3e603ee6bf2c3f7d,0xbd97bf133f46bf80,0xbf6a3f77bf5c3eac,0x3f5fbeb83dc93f0e,0x3e2fbf423f67bf78,0xbea13f58bf753f6d,0x3f80bf4a3f183d49,
0x3dfbbf393f62bf7b,0xbf7a3f65bf3e3e16,0x3f7fbf513f228000,0xbecfbe893f04bf71,0xbefc3f6fbf7f3f55,0x3f7cbf273edb3e79,0xbf733f09be95bec4,0x3cc93f1dbf4e3f80,
0x3f3ebf7d3f7bbf35,0xbf5c3edbbdc9bef1,0xbeacbe793f0ebf6d,0xbf4e3f80bf753f22,0xbd493f18bf553f80,0x3f78bf713f46be95,0x3f67bf043e483ec4,0x3e16bf2c3f62bf7f,
0x3f2cbe16be483f35,0x3f04bf673f7fbf62,0x3f71bf783f55bec4,0xbf183d493e95bf46,0xbf803f4ebf0e8000,0x3e793eacbf223f75,0xbedb3f5cbf7b3f6d,0x3f7dbf3e3ef13dc9,
0xbeb83f42bf753f7b,0x3f7ebf513f04bd49,0xbf7a3f77bf463ec4,0x3ee63cc9bedb3f4e,0xbf393ea13dc9bf0e,0xbefc3f58bf7d3f71,0x3e2fbf1d3f62bf80,0xbf7f3f6abf2c3e79,
0xbf6f3f27be95be48,0xbdfb3f13bf5c3f80,0xbe60be893f22bf6d,0xbf653f80bf673f18,0x3f31bf733f7fbf55,0xbf5f3f09be16beac,0x3f7cbf4a3ef18000,0xbd97becf3f3ebf78,
0xbe953f22bf6d3f80,0x3f7fbf623f0ebe48,0x3ef1bdc9bec43f35,0x3f46bf753f7bbf55,0x3f75bf463ec40000,0x3dc9bef13f55bf7b,0x3f62bf7f3f6dbf35,0xbf223e953e48bf0e,
0xbf753f46bec48000,0xbdc93ef1bf553f7b,0xbf623f7fbf6d3f35,0x3f22be95be483f0e,0xbe953f22bf6d3f80,0x3f7fbf623f0ebe48,0x3ef1bdc9bec43f35,0x3f46bf753f7bbf55,
0xbe2fbdfb3f22bf55,0xbf733f80bf5c3f2c,0x3ecfbf273f75bf80,0xbf773f58bedb3e16,0xbf7a3f5fbef13e48,0xbd973eb8bf4e3f71,0xbf313ee63dc9bec4,0xbf1d3f51bf803f78,
0x3f7cbf7e3f46bf0e,0xbea13cc93f04bf3e,0x3f6abf423e958000,0x3e89bf093f67bf7d,0x3e60befc3f62bf7b,0xbf7f3f6fbf183eac,0x3f39bf653f7fbf6d,0xbf4a3f13bd49be79,
0x3e79bd49bf0e3f35,0x3f71bf7d3f62bf46,0x3f18bedbbe483ec4,0x3f3ebf5c3f7fbf75,0xbf043f2cbf7b3f80,0x3f67bf4e3e95bdc9,0xbe163eacbf553f6d,0x3f80bf783f22bef1,
0xbf783f80bf553f35,0x3eacbe16bef13f22,0xbf4e3f67bf7b3f6d,0x3f2cbf04bdc93e95,0xbf5c3f3ebe488000,0xbedb3f18bf753f7f,0xbf7d3f71bf0e3ec4,0xbd493e79bf463f62,
0x3d97be2f3f46bf55,0xbf803f7ebf2c3f18,0x3e89beb83f62bf6d,0xbf7a3f73bf043edb,0x3ee6bf093f75bf7b,0xbf6a3f5fbeac3e79,0x3f1dbf313f7fbf80,0xbf513f42be163d49,
0x3f7fbf7c3f22bf0e,0x3cc9bdfb3f3ebf4e,0x3f77bf6f3ef1bec4,0x3e60bea13f5cbf67,0x3f65bf583e95be48,0x3ecfbefc3f71bf78,0x3f4abf393dc98000,0x3f13bf273f7dbf80,
0x3f35bf35bf803f80,0xbf353f3500000000,0x3f35bf35bf803f80,0xbf353f3500000000,0x3f35bf35bf803f80,0xbf353f3500000000,0x3f35bf35bf803f80,0xbf353f3500000000,
0x3f35bf3580008000,0x3f35bf35bf803f80,0x3f35bf3580008000,0x3f35bf35bf803f80,0x3f35bf3580008000,0x3f35bf35bf803f80,0x3f35bf3580008000,0x3f35bf35bf803f80,
0xbf65bf58bef1bf0e,0x3f6a3f5f3edb3f04,0xbf4abf39bf22bf35,0x3f513f423f183f2c,0xbf7fbf7cbdc9be48,0x3f803f7e3d493e16,0xbf77bf6fbe95bec4,0x3f7a3f733e793eac,
0xbee6bf093f623f55,0x3ecf3efcbf67bf5c,0xbf1dbf313f463f35,0x3f133f27bf4ebf3e,0xbd97be2f3f7f3f7b,0x3cc93dfbbf80bf7d,0xbe89beb83f753f6d,0x3e603ea1bf78bf71,
0x3f043f2cbf55bf35,0xbedbbf183f623f46,0x3e163eacbf7bbf6d,0xbd49be793f7f3f75,0x3f783f80be480000,0xbf71bf7d3e953dc9,0x3f4e3f67bf0ebec4,0xbf3ebf5c3f223ef1,
0xbf5cbf3ebf0ebf35,0x3f673f4e3ef13f22,0xbf7dbf71be48bec4,0x3f803f783dc93e95,0xbe79bd49bf7bbf80,0x3eac3e163f753f7f,0xbf18bedbbf55bf6d,0x3f2c3f043f463f62,
0x3f7a3f5f3e953f0e,0xbf7fbf6fbe16bedb,0x3f313ee63f463f6d,0xbf4abf13bf2cbf5c,0x3e2fbdfb3f7f3f7b,0xbea1bcc9bf78bf80,0xbecfbf273f623f35,0x3e893f09bf71bf4e,
0x3e603efcbf75bf55,0xbd97beb83f7d3f67,0x3f393f65bf22bec4,0xbf1dbf513f3e3f04,0x3f7c3f7ebdc93e48,0xbf73bf803e79bd49,0x3f6a3f423ef13f35,0xbf77bf58beacbf18,
0xbef1bdc9bf6dbf80,0x3f223e953f553f7b,0xbf75bf46bec4bf35,0x3f7f3f623e483f0e,0xbf62bf7f3ec40000,0x3f463f75bf0ebe48,0xbe95bf223f6d3f35,0x3dc93ef1bf7bbf55,
0xbf62bf7f3ec48000,0x3f463f75bf0ebe48,0xbe95bf223f6d3f35,0x3dc93ef1bf7bbf55,0x3ef13dc93f6d3f80,0xbf22be95bf55bf7b,0x3f753f463ec43f35,0xbf7fbf62be48bf0e,
0x3f313f73bf22be48,0xbefcbf583f4e3edb,0x3f7c3f4a3e953f35,0xbf7fbf6abd49bf04,0xbf6fbf27bef1bf55,0x3f7e3f513e793f2c,0xbe603e89bf7fbf6d,0x3ee6bcc93f713f7d,
0xbf39bea1bf46bf7b,0x3f5f3f093f183f67,0x3e2f3f1dbf75bf35,0x3d97becf3f803f5c,0xbeb8bf423f623f0e,0x3dfb3f13bf78bf3e,0xbf7abf773dc9bec4,0x3f653f80beac3e16,
0x3f803f4e3e483f35,0xbf78bf713dc9bef1,0x3edb3f5cbf55bec4,0xbe16bf2c3f753f22,0xbf3ebf7d3f0e0000,0x3f043f67bf46be95,0x3eacbe793f7b3f6d,0xbf18bd49bf62bf7f,
0x3d493f18bf7bbf35,0x3e79beac3f7f3f62,0xbf67bf04bf0ebf6d,0x3f7d3f3e3e953f46,0x3f2c3e163f553f80,0xbf5cbedbbf22bf75,0x3f713f78be483ec4,0xbf4ebf803ef1bdc9,
0x3f5f3eb83f223f7b,0xbf7cbf27beacbf5c,0xbea1bf583f623ec4,0xbcc93f1dbf7dbf2c,0xbf7ebf31be95bf55,0x3f7a3f65bd493f18,0xbd973f13bf7fbf35,0x3ecfbe893f783f67,
0x3efc3f6fbf46be48,0xbe2fbf423f713f04,0x3f733f093ef13f6d,0xbf80bf4abe16bf3e,0xbdfbbf393f753f0e,0xbe603ee6bf80bf4e,0xbf7fbf51bdc9bf35,0x3f6a3f77be793edb,
0x3f553e483f353f80,0xbf7bbf0ebec4bf6d,0x3f0e3f7bbf350000,0xbe48bf553f6d3ec4,0xbf55be48bf35bf80,0x3f7b3f0e3ec43f6d,0xbf0ebf7b3f350000,0x3e483f55bf6dbec4,
0x3f0e3f7bbf358000,0xbe48bf553f6d3ec4,0xbf55be48bf35bf80,0x3f7b3f0e3ec43f6d,0xbf0ebf7b3f358000,0x3e483f55bf6dbec4,0x3f553e483f353f80,0xbf7bbf0ebec4bf6d,
0x3efcbeb83f753f55,0xbf51bd97bf3ebf7d,0xbf73bf583dc9bf35,0x3f393f7ebf043eac,0xbf4abcc9bf46bf7b,0x3f7a3ee63edb3f78,0x3f423f7cbef13ec4,0xbecfbf773f4e3d49,
0x3f5f3f6fbe953f0e,0xbf13bf7f3f2cbe16,0x3ea1bf093f7f3f35,0xbf313dfbbf5cbf71,0xbf1dbf803f22be48,0x3e603f65bf67be79,0xbf273e2fbf62bf6d,0x3f6a3e893f183f80,
0x3edbbf043f7b3f35,0xbf4e3d49bf46bf75,0x3f2c3f7dbf0e3ec4,0xbe79bf713f623dc9,0x3eac3f78bf550000,0x3e16bf3e3f7f3ef1,0xbf80bf18be48bf6d,0x3f5c3f67be953f22,
0x3f673f5cbe483f35,0xbf18bf803f22be95,0xbf3e3e16bf55bf6d,0x3f783eac3ef13f7f,0xbf71be79bf0ebf80,0x3f7d3f2c3dc93f62,0x3d49bf4e3f7b3ec4,0xbf043edbbf75bf46,
0x3f31bea13f623f55,0xbf77be60bf04bf80,0xbf7cbf1dbdc9bf6d,0x3f423f6fbedb3f18,0x3ecf3f7fbf463e48,0x3dfbbf513f7d3eac,0x3f09befc3f753f35,0xbf65bcc9bf2cbf78,
0x3f393f73bef13f0e,0xbe89bf7a3f5cbd49,0x3e2fbf4a3f7f3ec4,0xbf273eb8bf67bf4e,0xbf6abd97bf22bf7b,0x3f7e3f133e163f71,0x3f583f5fbe953f35,0xbee6bf803f3ebe79,
0xbf7fbe95bec4bf80,0x3f623f46be483f55,0x3f22bef13f6d3f35,0xbf75bdc9bf0ebf7b,0x3dc93f75bf6d0000,0x3ef1bf223f7b3f0e,0xbf46bf623ec4bf35,0x3e953f7fbf553e48,
0xbdc9bf753f6d8000,0xbef13f22bf7bbf0e,0x3f463f62bec43f35,0xbe95bf7f3f55be48,0xbf7fbe95bec4bf80,0x3f623f46be483f55,0x3f22bef13f6d3f35,0xbf75bdc9bf0ebf7b,
0xbf7abefcbdc9bf7b,0x3f273f6abf043f2c,0x3f313f65bef13f35,0xbdfbbf7c3f67be16,0xbf133f1dbf75bf0e,0x3f73bcc93f183f71,0x3f6fbd973f223f6d,0xbf77bf09bd49bf78,
0x3e60bf5f3f7f3e48,0xbf423ecfbf5cbf3e,0xbf393ee6bf62bf35,0x3f7e3e2f3edb3f7d,0xbf51bf4a3e95bf55,0x3ea13f80bf4e3eac,0x3eb83f7fbf463ec4,0x3e89bf583f803e79,
0xbf18bf673f0ebf35,0xbd493f78bf753dc9,0x3f5c3f2cbe483f6d,0xbeacbf7d3f46bef1,0x3e16bf713f7b0000,0xbf3e3f04bf62bf22,0x3e793f80bf553ec4,0x3edbbf4e3f7f3e95,
0x3f4ebedb3f553f35,0xbf80be79be95bf7f,0xbf043f3ebf7bbec4,0x3f71be163f223f62,0x3f7d3eac3e483f80,0xbf2cbf5c3ef1bf46,0xbf783d49bf0ebf6d,0x3f673f18bdc93f75,
0x3ee6bf583f7f3e48,0xbf6f3e89bf2cbf4e,0xbf1d3f39bf75bec4,0x3f7cbd973f043f67,0x3f42bf133f623f0e,0xbf80bdfbbeacbf78,0xbf5f3ecfbf46bf35,0x3f7a3ea13e163f80,
0x3f653f09bdc93f7b,0xbeb8bf773f3ebf18,0xbf4abf313e95bf6d,0x3e2f3f7fbf5c3edb,0x3f273f51bef13f55,0x3cc9bf7e3f71be79,0xbefcbf6a3f22bf35,0xbe603f73bf7d3d49,
0x3f6d3ec400003f80,0xbec4bf6d3f35bf35,0xbf6dbec40000bf80,0x3ec43f6dbf353f35,0x3f6d3ec400003f80,0xbec4bf6d3f35bf35,0xbf6dbec40000bf80,0x3ec43f6dbf353f35,
0xbec43f6dbf808000,0x3f6dbec43f353f35,0x3ec4bf6d3f808000,0xbf6d3ec4bf35bf35,0xbec43f6dbf808000,0x3f6dbec43f353f35,0x3ec4bf6d3f808000,0xbf6d3ec4bf35bf35,
0x3d973f7cbf623f0e,0x3f31bf4a3f713e79,0xbe89bf6f3f46bf35,0xbf093f65bf7dbd49,0xbea13f7abf7f3e48,0x3f6abefc3f3e3f18,0x3dfbbf803f75bec4,0xbf513f27bf5cbedb,
0xbf7f3e2fbef1bf55,0x3f393f1dbeac3f78,0x3f77beb83f223f35,0xbf58bee63e16bf80,0xbf73be60bdc9bf7b,0x3ecf3f5fbf2c3f4e,0x3f7e3cc93e953f6d,0xbf13bf423f04bf67,
0xbf7d3eacbf0ebf35,0x3f3e3f04be953f7f,0x3f783d493e483f6d,0xbedbbf4e3f22bf62,0xbf183f67bf7b0000,0x3f80be793ef13f46,0x3f5cbf2c3f553ec4,0xbf71be16bdc9bf75,
0xbe16bf713f55bf35,0xbf2c3f5cbf75bdc9,0xbe793f80bf7b3ec4,0x3f67bf183f463ef1,0xbf4ebedb3e48bf80,0x3d493f78bf623f22,0x3f043f3ebf0e3f6d,0x3eacbf7d3f7fbe95,
0x3e2fbf7e3f75bf0e,0xbf653f31bf4ebeac,0x3ecf3f42bf223f6d,0x3efcbf7a3f80be79,0xbf58be893dc9bf7b,0x3d973f6fbf5c3f3e,0x3f80bea13ef13f35,0xbf1dbf133edbbf7d,
0x3f7cbdfb3e953f55,0xbee6bf393f18bf71,0xbf6a3f27bf46bec4,0x3f5f3e60bd493f78,0x3f09bf773f7fbe48,0xbf7f3eb8bf04bf2c,0x3cc93f73bf623f35,0x3f4abf513f673e16,
0xbf22bef13ec4bf80,0xbe953f7fbf7b3f0e,0xbdc93f75bf6d3f35,0x3f62bf463f553e48,0x3f46bf623f6d0000,0xbf753dc9be48bf55,0xbf7f3e95bec4bf35,0x3ef13f22bf0e3f7b,
0x3f46bf623f6d8000,0xbf753dc9be48bf55,0xbf7f3e95bec4bf35,0x3ef13f22bf0e3f7b,0x3f223ef1bec43f80,0x3e95bf7f3f7bbf0e,0x3dc9bf753f6dbf35,0xbf623f46bf55be48,
0x3f6fbf423f463e48,0xbf4abe2f3e16bf71,0xbe603f77bf753f35,0x3f73bf393f3e3e79,0xbcc93f65bf623f55,0x3f5fbf583f5c3d49,0xbf51bdfb3dc9bf6d,0xbd973f6abf673f4e,
0x3eb83f27bf223f7b,0x3f1dbf7c3f7dbeac,0xbf7a3e89be95bf35,0x3ea13f31bf2c3f78,0xbf803ee6bef1bf0e,0x3efc3f09bf043f80,0x3f13bf7e3f7fbec4,0xbf7f3ecfbedbbf18,
0xbeac3f78bf7b3f35,0x3f7dbf2c3f223e95,0x3f80bf183f0e3ec4,0xbf04bedb3ef1bf7f,0x3f67bf5c3f550000,0xbf4ebd493dc9bf62,0xbf3ebe163e48bf6d,0xbe793f71bf753f46,
0xbf713e79be48bf35,0x3e163f3ebf463f75,0x3d493f4ebf553f6d,0x3f5cbf673f62bdc9,0x3edb3f04bf0e3f80,0x3f18bf803f7fbef1,0x3f2cbf7d3f7bbec4,0xbf783eacbe95bf22,
0xbdfbbf313f46bf7b,0xbf583f73bf673e79,0x3f7fbf133ef13ec4,0xbeb8befc3f18bf80,0xbe893f6abf753f55,0x3f7cbf423f2c3e16,0xbf653e60bdc9bf35,0xbcc93f4abf5c3f71,
0x3f7ebf393f223e48,0xbf09bea13edbbf78,0xbd973f51bf623f6d,0x3f6fbf5f3f4ebd49,0xbf773ecfbe95bf0e,0x3e2f3f27bf3e3f7d,0x3ee6bf7a3f7fbf35,0xbf803f1dbf04beac,
0x3e483f0ebf353f80,0x3f55bf7b3f6dbec4,0x3f7bbf553f350000,0xbf0ebe483ec4bf6d,0xbe48bf0e3f35bf80,0xbf553f7bbf6d3ec4,0xbf7b3f55bf350000,0x3f0e3e48bec43f6d,
0xbf7b3f55bf358000,0x3f0e3e48bec43f6d,0x3e483f0ebf353f80,0x3f55bf7b3f6dbec4,0x3f7bbf553f358000,0xbf0ebe483ec4bf6d,0xbe48bf0e3f35bf80,0xbf553f7bbf6d3ec4,
0xbf1dbcc93e95bf55,0xbf093f73bf803f4e,0x3f27bf7c3f7fbf35,0xbf6f3efcbe79bedb,0x3e893ecfbf223f7b,0x3f51bf7f3f71bf04,0xbf653f7abf623ec4,0x3f39bdfbbe163f3e,
0x3f4abf803f75bf0e,0xbf583ea1bd49bf18,0x3f42be2fbdc93f35,0x3eb8bf5f3f78bf67,0xbf773f6abf463e48,0x3f133d97beac3f5c,0xbee6be603ef1bf6d,0xbf313f7ebf7d3f2c,
0x3f2cbe16be483f35,0x3f04bf673f7fbf62,0x3f71bf783f55bec4,0xbf183d493e95bf46,0xbf803f4ebf0e0000,0x3e793eacbf223f75,0xbedb3f5cbf7b3f6d,0x3f7dbf3e3ef13dc9,
0xbf3e3f7dbf7b3f35,0x3f5cbedb3dc93ef1,0x3eac3e79bf0e3f6d,0x3f4ebf803f75bf22,0x3d49bf183f55bf80,0xbf783f71bf463e95,0xbf673f04be48bec4,0xbe163f2cbf623f7f,
0xbecfbd973ef1bf55,0xbf4a3f7cbf783f3e,0x3f09bf5f3f7fbf6d,0xbf733f31beacbe16,0x3f80bf653f22be48,0xbe89be603f18bf67,0x3f13bdfbbe953f35,0x3f27bf6f3f80bf5c,
0x3f6abf7f3f62bf0e,0xbf1d3e2f3e79bf2c,0x3f58befc3dc93ec4,0x3ea1bf393f71bf7d,0x3cc93ee6bf463f7b,0x3f77bf7a3f4ebedb,0xbf513f7ebf753f35,0x3f42beb8bd493f04,
0x3e95bf223f6dbf80,0xbf7f3f62bf0e3e48,0xbef13dc93ec4bf35,0xbf463f75bf7b3f55,0xbf753f46bec40000,0xbdc93ef1bf553f7b,0xbf623f7fbf6d3f35,0x3f22be95be483f0e,
0x3f75bf463ec48000,0x3dc9bef13f55bf7b,0x3f62bf7f3f6dbf35,0xbf223e953e48bf0e,0x3e95bf223f6dbf80,0xbf7f3f62bf0e3e48,0xbef13dc93ec4bf35,0xbf463f75bf7b3f55,
0xbf133f4abf7f3f7b,0x3f65bf393e793d49,0xbf6f3f7fbf623f35,0x3efcbe60beac3f18,0x3f09be89be953f0e,0x3f42bf6a3f7dbf67,0xbcc93ea1bf463f6d,0x3f7ebf7c3f3ebf04,
0xbf513f1dbdc9be48,0xbee63f31bf783f80,0xbeb83d973ef1bf35,0xbf5f3f7abf713f4e,0xbf583f77bf753f55,0x3f27becfbe163edb,0xbf803f73bf223ec4,0x3dfb3e2fbf2c3f5c,
0x3f78bf803f55bf35,0xbeac3e163ef1bf22,0x3f4ebf673f7bbf6d,0xbf2c3f043dc9be95,0x3f5cbf3e3e480000,0x3edbbf183f75bf7f,0x3f7dbf713f0ebec4,0x3d49be793f46bf62,
0x3e79bd49bf0e3f35,0x3f71bf7d3f62bf46,0x3f18bedbbe483ec4,0x3f3ebf5c3f7fbf75,0xbf043f2cbf7b3f80,0x3f67bf4e3e95bdc9,0xbe163eacbf553f6d,0x3f80bf783f22bef1,
0xbf273f133dc9be48,0xbf393f4abf803f7d,0xbefc3ecf3e95bec4,0xbf583f65bf783f71,0xbea13e603ef1bf0e,0xbf6f3f77bf673f5c,0xbdfb3cc93f22bf35,0xbf7c3f7fbf4e3f3e,
0x3f42bf513f7fbf7b,0xbf313f1d3d49be16,0x3f5fbf6a3f75bf6d,0xbf093ee63e79beac,0x3f73bf7a3f62bf55,0xbeb83e893edbbf04,0x3f7ebf803f46bf35,0xbe2f3d973f18bf2c,
0x3f35bf35bf803f80,0xbf353f3500000000,0x3f35bf35bf803f80,0xbf353f3500000000,0x3f35bf35bf803f80,0xbf353f3500000000,0x3f35bf35bf803f80,0xbf353f3500000000,
0x3f35bf3580008000,0x3f35bf35bf803f80,0x3f35bf3580008000,0x3f35bf35bf803f80,0x3f35bf3580008000,0x3f35bf35bf803f80,0x3f35bf3580008000,0x3f35bf35bf803f80,
0xbf73bf7a3e953e48,0x3f6f3f77beacbe79,0xbf7ebf803dc90000,0x3f7c3f7fbe16bd49,0xbf42bf513f223f0e,0x3f393f4abf2cbf18,0xbf5fbf6a3ef13ec4,0x3f583f65bf04bedb,
0x3ea13e603f753f7b,0xbeb8be89bf71bf78,0x3dfb3cc93f7f3f80,0xbe2fbd97bf7dbf80,0x3f273f133f463f55,0xbf31bf1dbf3ebf4e,0x3efc3ecf3f623f6d,0xbf09bee6bf5cbf67,
0xbf5cbf3ebf0ebf35,0x3f673f4e3ef13f22,0xbf7dbf71be48bec4,0x3f803f783dc93e95,0xbe79bd49bf7bbf80,0x3eac3e163f753f7f,0xbf18bedbbf55bf6d,0x3f2c3f043f463f62,
0xbf04bf2c3f553f35,0x3edb3f18bf62bf46,0xbe16beac3f7b3f6d,0x3d493e79bf7fbf75,0xbf78bf803e488000,0x3f713f7dbe95bdc9,0xbf4ebf673f0e3ec4,0x3f3e3f5cbf22bef1,
0xbf09be89bf62bf7b,0x3f273ecf3f4e3f71,0x3cc93ea1bf7fbf6d,0x3dfbbe2f3f803f78,0x3f133f4abf46bf0e,0xbee6bf313f5c3f2c,0x3f6f3f7fbe950000,0xbf5fbf7a3edb3e16,
0xbf58bf773ef13e48,0x3f423f6abf18beac,0xbf80bf73bdc9bec4,0x3f7e3f7cbd493e79,0xbf51bf1dbf22bf55,0x3f653f393f043f3e,0xbeb8bd97bf75bf80,0x3efc3e603f673f7d,
0x3ef13dc93f6d3f80,0xbf22be95bf55bf7b,0x3f753f463ec43f35,0xbf7fbf62be48bf0e,0x3f623f7fbec40000,0xbf46bf753f0e3e48,0x3e953f22bf6dbf35,0xbdc9bef13f7b3f55,
0x3f623f7fbec48000,0xbf46bf753f0e3e48,0x3e953f22bf6dbf35,0xbdc9bef13f7b3f55,0xbef1bdc9bf6dbf80,0x3f223e953f553f7b,0xbf75bf46bec4bf35,0x3f7f3f623e483f0e,
0x3cc9bee63f7f3f55,0xbe893e60bf7dbf71,0xbf51bf7e3ef10000,0x3f273f6fbf2cbe79,0x3f6a3f7fbe953e48,0xbf4abf7c3f043d49,0x3f583efc3f223f6d,0xbf73bf31bedbbf4e,
0x3f803f653dc93f0e,0xbf77bf7a3e16beac,0x3f133dfb3f623f80,0xbf42beb8bf3ebf78,0xbecf3d97bf75bf7b,0x3f1d3e2f3f5c3f80,0x3f093f5fbf46bec4,0xbea1bf393f673f18,
0xbd49bf183f7b3f35,0xbe793eacbf7fbf62,0x3f673f043f0e3f6d,0xbf7dbf3ebe95bf46,0xbf2cbe16bf55bf80,0x3f5c3edb3f223f75,0xbf71bf783e48bec4,0x3f4e3f80bef13dc9,
0x3f803f4e3e483f35,0xbf78bf713dc9bef1,0x3edb3f5cbf55bec4,0xbe16bf2c3f753f22,0xbf3ebf7d3f0e8000,0x3f043f67bf46be95,0x3eacbe793f7b3f6d,0xbf18bd49bf62bf7f,
0x3e89becf3f7f3f55,0xbf133d97bf67bf78,0xbf65bf7a3e95bec4,0x3f313f7ebf183d49,0xbf1d3cc9bf62bf7b,0x3f583ea13f2c3f7d,0x3f273f7cbf220000,0xbeb8bf5f3f5c3eac,
0x3f773f6abdc93f0e,0xbf51bf7f3edbbe79,0x3ee6be603f753f6d,0xbf39bdfbbf4ebf80,0xbf4abf803ef1be48,0x3f093f73bf3ebe16,0xbf42be2fbf46bf80,0x3f6f3efc3f043f71,
0x3f553e483f353f80,0xbf7bbf0ebec4bf6d,0x3f0e3f7bbf350000,0xbe48bf553f6d3ec4,0xbf55be48bf35bf80,0x3f7b3f0e3ec43f6d,0xbf0ebf7b3f350000,0x3e483f55bf6dbec4,
0x3f0e3f7bbf358000,0xbe48bf553f6d3ec4,0xbf55be48bf35bf80,0x3f7b3f0e3ec43f6d,0xbf0ebf7b3f358000,0x3e483f55bf6dbec4,0x3f553e483f353f80,0xbf7bbf0ebec4bf6d,
0x3f773ecf3ef13f7b,0xbf7cbf42bd49bf4e,0xbee6bf7a3f460000,0x3cc93f4abf78bedb,0xbf7ebf39bdc9bf55,0x3f583f73beac3f04,0x3d973f51bf75bec4,0x3eb8befc3f7d3f3e,
0x3e893f6abf62be48,0x3e2fbf273f803f18,0x3f653e603f223f80,0xbf80bf1dbe79bf67,0x3dfbbf313f7f3f0e,0xbf093ea1bf71bf5c,0xbf7fbf13be95bf6d,0x3f6f3f5fbe163f2c,
0x3f673f5cbe483f35,0xbf18bf803f22be95,0xbf3e3e16bf55bf6d,0x3f783eac3ef13f7f,0xbf71be79bf0ebf80,0x3f7d3f2c3dc93f62,0x3d49bf4e3f7b3ec4,0xbf043edbbf75bf46,
0xbedb3f04bf7bbf35,0x3f4ebd493f463f75,0xbf2cbf7d3f0ebec4,0x3e793f71bf62bdc9,0xbeacbf783f558000,0xbe163f3ebf7fbef1,0x3f803f183e483f6d,0xbf5cbf673e95bf22,
0x3cc93f65bf75be48,0x3efcbf093f783f2c,0x3f51bdfb3f463f6d,0xbf7fbecfbeacbf7d,0xbf6fbf423dc9bf55,0x3f1d3f7cbf183edb,0x3e603f77bf620000,0x3ea1bf313f803f04,
0xbf80bee6be95bf7b,0x3f5f3f58be793f3e,0x3f133f7ebf223ec4,0xbd97bf6a3f713e16,0x3eb8bf273f7f3f0e,0xbf4a3e2fbf4ebf67,0xbf7abe89bef1bf80,0x3f733f39bd493f5c,
0x3f7f3e953ec43f80,0xbf62bf463e48bf55,0xbf223ef1bf6dbf35,0x3f753dc93f0e3f7b,0xbdc9bf753f6d0000,0xbef13f22bf7bbf0e,0x3f463f62bec43f35,0xbe95bf7f3f55be48,
0x3dc93f75bf6d8000,0x3ef1bf223f7b3f0e,0xbf46bf623ec4bf35,0x3e953f7fbf553e48,0x3f7f3e953ec43f80,0xbf62bf463e48bf55,0xbf223ef1bf6dbf35,0x3f753dc93f0e3f7b,
0x3f093f77bf223f0e,0x3d97bf6f3f783d49,0x3cc9bf733f750000,0xbf1d3f13bf71bf18,0x3f7c3dfb3ef13f7b,0xbf65bf313e16bf67,0xbf6abf273dc9bf6d,0x3efc3f7abf2c3f04,
0xbf583e89bf46bf55,0x3f7f3eb83e793f80,0x3f803ea13e953f80,0xbf4abf513eacbf4e,0x3e2f3f7ebf623e48,0x3ee6bf393f7d3edb,0x3ecfbf423f7f3ec4,0xbf5f3e60bf3ebf5c,
0xbf4e3edbbf55bf35,0x3f803e793e953f7f,0x3f04bf3e3f7b3ec4,0xbf713e16bf22bf62,0xbf7dbeacbe48bf80,0x3f2c3f5cbef13f46,0x3f78bd493f0e3f6d,0xbf67bf183dc9bf75,
0xbf18bf673f0ebf35,0xbd493f78bf753dc9,0x3f5c3f2cbe483f6d,0xbeacbf7d3f46bef1,0x3e16bf713f7b8000,0xbf3e3f04bf62bf22,0x3e793f80bf553ec4,0x3edbbf4e3f7f3e95,
0xbea1bf7a3f46bf0e,0xbecf3f5fbf80be16,0x3dfb3f80bf623ec4,0x3f13bf423f783eac,0x3d97bf7c3f75be48,0xbf393f1dbf67bf04,0xbe893f6fbf7f0000,0x3f58bee63f4e3f2c,
0x3f73be603f223f55,0xbf6abefc3d49bf7d,0xbf7e3cc9bef1bf6d,0x3f513f27be793f71,0x3f7f3e2f3e953f7b,0xbf31bf4a3edbbf5c,0xbf77beb8bdc9bf80,0x3f093f65bf183f3e,
0x3f6d3ec400003f80,0xbec4bf6d3f35bf35,0xbf6dbec40000bf80,0x3ec43f6dbf353f35,0x3f6d3ec400003f80,0xbec4bf6d3f35bf35,0xbf6dbec40000bf80,0x3ec43f6dbf353f35,
0xbec43f6dbf808000,0x3f6dbec43f353f35,0x3ec4bf6d3f808000,0xbf6d3ec4bf35bf35,0xbec43f6dbf808000,0x3f6dbec43f353f35,0x3ec4bf6d3f808000,0xbf6d3ec4bf35bf35,
0xbf273f51bf75be48,0x3f80bdfb3edb3f5c,0x3efcbf6a3f7f0000,0xbf7a3ea1bf18bf3e,0xbf653f09bf46bf0e,0x3f6f3e893d493f7d,0x3f4abf313f623ec4,0xbf7cbd97be79bf71,
0xbf42bf133e95bf7b,0x3cc93f7ebf673f04,0x3f5f3ecfbdc93f80,0xbe60bf733f4ebf2c,0xbee6bf583f22bf55,0xbeb83f77bf803e16,0x3f1d3f39bef13f6d,0x3e2fbf7f3f78beac,
0xbe16bf713f55bf35,0xbf2c3f5cbf75bdc9,0xbe793f80bf7b3ec4,0x3f67bf183f463ef1,0xbf4ebedb3e48bf80,0x3d493f78bf623f22,0x3f043f3ebf0e3f6d,0x3eacbf7d3f7fbe95,
0x3f7dbeac3f0e3f35,0xbf3ebf043e95bf7f,0xbf78bd49be48bf6d,0x3edb3f4ebf223f62,0x3f18bf673f7b8000,0xbf803e79bef1bf46,0xbf5c3f2cbf55bec4,0x3f713e163dc93f75,
0x3f133f1dbef13f7b,0x3ea1bf803f7dbedb,0xbf6fbd97bdc9bf6d,0x3e893f58bf3e3f5c,0x3f7abefc3f223f0e,0xbf42becf3e79bf80,0xbf313f65bf750000,0x3f7ebe2f3eac3f4e,
0xbf513f4abf62be48,0x3f733cc93e163f67,0x3eb8bf7f3f7fbec4,0xbf773f09bf2cbf04,0x3e603f5fbf463f55,0x3f27bf6a3f78bd49,0xbf39bee63e95bf80,0xbdfb3f7cbf713f18,
0x3f223ef1bec43f80,0x3e95bf7f3f7bbf0e,0x3dc9bf753f6dbf35,0xbf623f46bf55be48,0xbf463f62bf6d0000,0x3f75bdc93e483f55,0x3f7fbe953ec43f35,0xbef1bf223f0ebf7b,
0xbf463f62bf6d8000,0x3f75bdc93e483f55,0x3f7fbe953ec43f35,0xbef1bf223f0ebf7b,0xbf22bef13ec4bf80,0xbe953f7fbf7b3f0e,0xbdc93f75bf6d3f35,0x3f62bf463f553e48,
0xbf6a3d97bdc9bf55,0x3dfb3f51bf4e3f67,0x3f58bf5f3f620000,0xbf653cc9bd49bf5c,0x3f39bf733f75be48,0xbf773e60be79bf3e,0x3e2f3f4abf463f6d,0x3f42bf6f3f71be16,
0x3ecfbf7f3f7fbf0e,0xbf7e3f13bf18bedb,0x3f093efcbef13f80,0x3ee6bf803f80bf04,0x3f313ea1be953f7b,0x3e89bf7a3f78bf2c,0xbf7c3f1dbf22bec4,0x3f273eb8beac3f7d,
0x3f71be793e483f35,0xbe16bf3e3f46bf75,0xbd49bf4e3f55bf6d,0xbf5c3f67bf623dc9,0xbedbbf043f0ebf80,0xbf183f80bf7f3ef1,0xbf2c3f7dbf7b3ec4,0x3f78beac3e953f22,
0xbeac3f78bf7b3f35,0x3f7dbf2c3f223e95,0x3f80bf183f0e3ec4,0xbf04bedb3ef1bf7f,0x3f67bf5c3f558000,0xbf4ebd493dc9bf62,0xbf3ebe163e48bf6d,0xbe793f71bf753f46,
0xbf4a3cc93dc9bf55,0xbe603f65bf713f5c,0x3f42bf7c3f75bec4,0xbf6a3e89be16bf2c,0x3efc3eb8bef13f7b,0x3f13bf7f3f80bf18,0xbf733f58bf460000,0x3f313dfbbe793f67,
0x3f1dbf803f7fbf0e,0xbf7a3ee6beacbf04,0x3f273e2fbe953f6d,0x3ecfbf773f7dbf3e,0xbf5f3f6fbf623e48,0x3f51bd97bd493f4e,0xbea1bf093f22bf80,0xbf393f7ebf783edb,
0x3e483f0ebf353f80,0x3f55bf7b3f6dbec4,0x3f7bbf553f350000,0xbf0ebe483ec4bf6d,0xbe48bf0e3f35bf80,0xbf553f7bbf6d3ec4,0xbf7b3f55bf350000,0x3f0e3e48bec43f6d,
0xbf7b3f55bf358000,0x3f0e3e48bec43f6d,0x3e483f0ebf353f80,0x3f55bf7b3f6dbec4,0x3f7bbf553f358000,0xbf0ebe483ec4bf6d,0xbe48bf0e3f35bf80,0xbf553f7bbf6d3ec4,
0x3dfbbf393f62bf7b,0xbf7a3f65bf3e3e16,0x3f7fbf513f220000,0xbecfbe893f04bf71,0xbefc3f6fbf7f3f55,0x3f7cbf273edb3e79,0xbf733f09be95bec4,0x3cc93f1dbf4e3f80,
0x3f7ebf313ef13e48,0xbe60bee63f2cbf7d,0x3d973f13bf463f80,0x3f6abf773f5cbeac,0xbf5f3eb8bdc9bf0e,0xbe2f3f42bf673f78,0x3ea1bf583f75bf6d,0xbf803f4abf18bd49,
0xbf3e3f7dbf7b3f35,0x3f5cbedb3dc93ef1,0x3eac3e79bf0e3f6d,0x3f4ebf803f75bf22,0x3d49bf183f55bf80,0xbf783f71bf463e95,0xbf673f04be48bec4,0xbe163f2cbf623f7f,
0xbf2c3e163e48bf35,0xbf043f67bf7f3f62,0xbf713f78bf553ec4,0x3f18bd49be953f46,0x3f80bf4e3f0e8000,0xbe79beac3f22bf75,0x3edbbf5c3f7bbf6d,0xbf7d3f3ebef1bdc9,
0x3f6fbf273e953e48,0x3dfbbf133f5cbf80,0x3e603e89bf223f6d,0x3f65bf803f67bf18,0xbf313f73bf7f3f55,0x3f5fbf093e163eac,0xbf7c3f4abef10000,0x3d973ecfbf3e3f78,
0xbeb83f42bf753f7b,0x3f7ebf513f04bd49,0xbf7a3f77bf463ec4,0x3ee63cc9bedb3f4e,0xbf393ea13dc9bf0e,0xbefc3f58bf7d3f71,0x3e2fbf1d3f62bf80,0xbf7f3f6abf2c3e79,
0xbe953f22bf6d3f80,0x3f7fbf623f0ebe48,0x3ef1bdc9bec43f35,0x3f46bf753f7bbf55,0x3f75bf463ec40000,0x3dc9bef13f55bf7b,0x3f62bf7f3f6dbf35,0xbf223e953e48bf0e,
0xbf753f46bec48000,0xbdc93ef1bf553f7b,0xbf623f7fbf6d3f35,0x3f22be95be483f0e,0xbe953f22bf6d3f80,0x3f7fbf623f0ebe48,0x3ef1bdc9bec43f35,0x3f46bf753f7bbf55,
0x3f7cbf7e3f46bf0e,0xbea13cc93f04bf3e,0x3f6abf423e950000,0x3e89bf093f67bf7d,0x3e60befc3f62bf7b,0xbf7f3f6fbf183eac,0x3f39bf653f7fbf6d,0xbf4a3f13bd49be79,
0x3e2f3dfbbf223f55,0x3f73bf803f5cbf2c,0xbecf3f27bf753f80,0x3f77bf583edbbe16,0x3f7abf5f3ef1be48,0x3d97beb83f4ebf71,0x3f31bee6bdc93ec4,0x3f1dbf513f80bf78,
0xbe793d493f0ebf35,0xbf713f7dbf623f46,0xbf183edb3e48bec4,0xbf3e3f5cbf7f3f75,0x3f04bf2c3f7bbf80,0xbf673f4ebe953dc9,0x3e16beac3f55bf6d,0xbf803f78bf223ef1,
0x3f78bf803f55bf35,0xbeac3e163ef1bf22,0x3f4ebf673f7bbf6d,0xbf2c3f043dc9be95,0x3f5cbf3e3e488000,0x3edbbf183f75bf7f,0x3f7dbf713f0ebec4,0x3d49be793f46bf62,
0xbf7f3f7cbf223f0e,0xbcc93dfbbf3e3f4e,0xbf773f6fbef13ec4,0xbe603ea1bf5c3f67,0xbf653f58be953e48,0xbecf3efcbf713f78,0xbf4a3f39bdc90000,0xbf133f27bf7d3f80,
0x3d97be2f3f46bf55,0xbf803f7ebf2c3f18,0x3e89beb83f62bf6d,0xbf7a3f73bf043edb,0x3ee6bf093f75bf7b,0xbf6a3f5fbeac3e79,0x3f1dbf313f7fbf80,0xbf513f42be163d49,
0x3f35bf35bf803f80,0xbf353f3500000000,0x3f35bf35bf803f80,0xbf353f3500000000,0x3f35bf35bf803f80,0xbf353f3500000000,0x3f35bf35bf803f80,0xbf353f3500000000,
0x3f35bf3580008000,0x3f35bf35bf803f80,0x3f35bf3580008000,0x3f35bf35bf803f80,0x3f35bf3580008000,0x3f35bf35bf803f80,0x3f35bf3580008000,0x3f35bf35bf803f80,
0xbee6bf093f623f55,0x3ecf3efcbf67bf5c,0xbf1dbf313f463f35,0x3f133f27bf4ebf3e,0xbd97be2f3f7f3f7b,0x3cc93dfbbf80bf7d,0xbe89beb83f753f6d,0x3e603ea1bf78bf71,
0x3f653f583ef13f0e,0xbf6abf5fbedbbf04,0x3f4a3f393f223f35,0xbf51bf42bf18bf2c,0x3f7f3f7c3dc93e48,0xbf80bf7ebd49be16,0x3f773f6f3e953ec4,0xbf7abf73be79beac,
0xbf04bf2c3f553f35,0x3edb3f18bf62bf46,0xbe16beac3f7b3f6d,0x3d493e79bf7fbf75,0xbf78bf803e480000,0x3f713f7dbe95bdc9,0xbf4ebf673f0e3ec4,0x3f3e3f5cbf22bef1,
0x3f5c3f3e3f0e3f35,0xbf67bf4ebef1bf22,0x3f7d3f713e483ec4,0xbf80bf78bdc9be95,0x3e793d493f7b3f80,0xbeacbe16bf75bf7f,0x3f183edb3f553f6d,0xbf2cbf04bf46bf62,
0xbe60befc3f753f55,0x3d973eb8bf7dbf67,0xbf39bf653f223ec4,0x3f1d3f51bf3ebf04,0xbf7cbf7e3dc9be48,0x3f733f80be793d49,0xbf6abf42bef1bf35,0x3f773f583eac3f18,
0x3f7a3f5f3e953f0e,0xbf7fbf6fbe16bedb,0x3f313ee63f463f6d,0xbf4abf13bf2cbf5c,0x3e2fbdfb3f7f3f7b,0xbea1bcc9bf78bf80,0xbecfbf273f623f35,0x3e893f09bf71bf4e,
0xbef1bdc9bf6dbf80,0x3f223e953f553f7b,0xbf75bf46bec4bf35,0x3f7f3f623e483f0e,0xbf62bf7f3ec40000,0x3f463f75bf0ebe48,0xbe95bf223f6d3f35,0x3dc93ef1bf7bbf55,
0xbf62bf7f3ec48000,0x3f463f75bf0ebe48,0xbe95bf223f6d3f35,0x3dc93ef1bf7bbf55,0x3ef13dc93f6d3f80,0xbf22be95bf55bf7b,0x3f753f463ec43f35,0xbf7fbf62be48bf0e,
0xbf39bea1bf46bf7b,0x3f5f3f093f183f67,0x3e2f3f1dbf75bf35,0x3d97becf3f803f5c,0xbeb8bf423f623f0e,0x3dfb3f13bf78bf3e,0xbf7abf773dc9bec4,0x3f653f80beac3e16,
0xbf31bf733f223e48,0x3efc3f58bf4ebedb,0xbf7cbf4abe95bf35,0x3f7f3f6a3d493f04,0x3f6f3f273ef13f55,0xbf7ebf51be79bf2c,0x3e60be893f7f3f6d,0xbee63cc9bf71bf7d,
0xbf80bf4ebe48bf35,0x3f783f71bdc93ef1,0xbedbbf5c3f553ec4,0x3e163f2cbf75bf22,0x3f3e3f7dbf0e0000,0xbf04bf673f463e95,0xbeac3e79bf7bbf6d,0x3f183d493f623f7f,
0xbd49bf183f7b3f35,0xbe793eacbf7fbf62,0x3f673f043f0e3f6d,0xbf7dbf3ebe95bf46,0xbf2cbe16bf55bf80,0x3f5c3edb3f223f75,0xbf71bf783e48bec4,0x3f4e3f80bef13dc9,
0xbefcbf6f3f463e48,0x3e2f3f42bf71bf04,0xbf73bf09bef1bf6d,0x3f803f4a3e163f3e,0x3dfb3f39bf75bf0e,0x3e60bee63f803f4e,0x3f7f3f513dc93f35,0xbf6abf773e79bedb,
0x3f5f3eb83f223f7b,0xbf7cbf27beacbf5c,0xbea1bf583f623ec4,0xbcc93f1dbf7dbf2c,0xbf7ebf31be95bf55,0x3f7a3f65bd493f18,0xbd973f13bf7fbf35,0x3ecfbe893f783f67,
0x3f553e483f353f80,0xbf7bbf0ebec4bf6d,0x3f0e3f7bbf350000,0xbe48bf553f6d3ec4,0xbf55be48bf35bf80,0x3f7b3f0e3ec43f6d,0xbf0ebf7b3f350000,0x3e483f55bf6dbec4,
0x3f0e3f7bbf358000,0xbe48bf553f6d3ec4,0xbf55be48bf35bf80,0x3f7b3f0e3ec43f6d,0xbf0ebf7b3f358000,0x3e483f55bf6dbec4,0x3f553e483f353f80,0xbf7bbf0ebec4bf6d,
0x3f5f3f6fbe953f0e,0xbf13bf7f3f2cbe16,0x3ea1bf093f7f3f35,0xbf313dfbbf5cbf71,0xbf1dbf803f22be48,0x3e603f65bf67be79,0xbf273e2fbf62bf6d,0x3f6a3e893f183f80,
0xbefc3eb8bf75bf55,0x3f513d973f3e3f7d,0x3f733f58bdc93f35,0xbf39bf7e3f04beac,0x3f4a3cc93f463f7b,0xbf7abee6bedbbf78,0xbf42bf7c3ef1bec4,0x3ecf3f77bf4ebd49,
0xbedb3f04bf7bbf35,0x3f4ebd493f463f75,0xbf2cbf7d3f0ebec4,0x3e793f71bf62bdc9,0xbeacbf783f550000,0xbe163f3ebf7fbef1,0x3f803f183e483f6d,0xbf5cbf673e95bf22,
0xbf67bf5c3e48bf35,0x3f183f80bf223e95,0x3f3ebe163f553f6d,0xbf78beacbef1bf7f,0x3f713e793f0e3f80,0xbf7dbf2cbdc9bf62,0xbd493f4ebf7bbec4,0x3f04bedb3f753f46,
0xbf39bf733ef1bf0e,0x3e893f7abf5c3d49,0xbe2f3f4abf7fbec4,0x3f27beb83f673f4e,0x3f6a3d973f223f7b,0xbf7ebf13be16bf71,0xbf58bf5f3e95bf35,0x3ee63f80bf3e3e79,
0x3f31bea13f623f55,0xbf77be60bf04bf80,0xbf7cbf1dbdc9bf6d,0x3f423f6fbedb3f18,0x3ecf3f7fbf463e48,0x3dfbbf513f7d3eac,0x3f09befc3f753f35,0xbf65bcc9bf2cbf78,
0xbf7fbe95bec4bf80,0x3f623f46be483f55,0x3f22bef13f6d3f35,0xbf75bdc9bf0ebf7b,0x3dc93f75bf6d0000,0x3ef1bf223f7b3f0e,0xbf46bf623ec4bf35,0x3e953f7fbf553e48,
0xbdc9bf753f6d8000,0xbef13f22bf7bbf0e,0x3f463f62bec43f35,0xbe95bf7f3f55be48,0xbf7fbe95bec4bf80,0x3f623f46be483f55,0x3f22bef13f6d3f35,0xbf75bdc9bf0ebf7b,
0x3e60bf5f3f7f3e48,0xbf423ecfbf5cbf3e,0xbf393ee6bf62bf35,0x3f7e3e2f3edb3f7d,0xbf51bf4a3e95bf55,0x3ea13f80bf4e3eac,0x3eb83f7fbf463ec4,0x3e89bf583f803e79,
0x3f7a3efc3dc93f7b,0xbf27bf6a3f04bf2c,0xbf31bf653ef1bf35,0x3dfb3f7cbf673e16,0x3f13bf1d3f753f0e,0xbf733cc9bf18bf71,0xbf6f3d97bf22bf6d,0x3f773f093d493f78,
0x3f183f67bf0e3f35,0x3d49bf783f75bdc9,0xbf5cbf2c3e48bf6d,0x3eac3f7dbf463ef1,0xbe163f71bf7b0000,0x3f3ebf043f623f22,0xbe79bf803f55bec4,0xbedb3f4ebf7fbe95,
0xbf4e3edbbf55bf35,0x3f803e793e953f7f,0x3f04bf3e3f7b3ec4,0xbf713e16bf22bf62,0xbf7dbeacbe48bf80,0x3f2c3f5cbef13f46,0x3f78bd493f0e3f6d,0xbf67bf183dc9bf75,
0xbf65bf093dc9bf7b,0x3eb83f77bf3e3f18,0x3f4a3f31be953f6d,0xbe2fbf7f3f5cbedb,0xbf27bf513ef1bf55,0xbcc93f7ebf713e79,0x3efc3f6abf223f35,0x3e60bf733f7dbd49,
0x3ee6bf583f7f3e48,0xbf6f3e89bf2cbf4e,0xbf1d3f39bf75bec4,0x3f7cbd973f043f67,0x3f42bf133f623f0e,0xbf80bdfbbeacbf78,0xbf5f3ecfbf46bf35,0x3f7a3ea13e163f80,
0x3f6d3ec400003f80,0xbec4bf6d3f35bf35,0xbf6dbec40000bf80,0x3ec43f6dbf353f35,0x3f6d3ec400003f80,0xbec4bf6d3f35bf35,0xbf6dbec40000bf80,0x3ec43f6dbf353f35,
0xbec43f6dbf808000,0x3f6dbec43f353f35,0x3ec4bf6d3f808000,0xbf6d3ec4bf35bf35,0xbec43f6dbf808000,0x3f6dbec43f353f35,0x3ec4bf6d3f808000,0xbf6d3ec4bf35bf35,
0xbf7f3e2fbef1bf55,0x3f393f1dbeac3f78,0x3f77beb83f223f35,0xbf58bee63e16bf80,0xbf73be60bdc9bf7b,0x3ecf3f5fbf2c3f4e,0x3f7e3cc93e953f6d,0xbf13bf423f04bf67,
0xbd97bf7c3f62bf0e,0xbf313f4abf71be79,0x3e893f6fbf463f35,0x3f09bf653f7d3d49,0x3ea1bf7a3f7fbe48,0xbf6a3efcbf3ebf18,0xbdfb3f80bf753ec4,0x3f51bf273f5c3edb,
0x3f7dbeac3f0e3f35,0xbf3ebf043e95bf7f,0xbf78bd49be48bf6d,0x3edb3f4ebf223f62,0x3f18bf673f7b0000,0xbf803e79bef1bf46,0xbf5c3f2cbf55bec4,0x3f713e163dc93f75,
0x3e163f71bf553f35,0x3f2cbf5c3f753dc9,0x3e79bf803f7bbec4,0xbf673f18bf46bef1,0x3f4e3edbbe483f80,0xbd49bf783f62bf22,0xbf04bf3e3f0ebf6d,0xbeac3f7dbf7f3e95,
0xbf7c3dfbbe95bf55,0x3ee63f39bf183f71,0x3f6abf273f463ec4,0xbf5fbe603d49bf78,0xbf093f77bf7f3e48,0x3f7fbeb83f043f2c,0xbcc9bf733f62bf35,0xbf4a3f51bf67be16,
0x3e2fbf7e3f75bf0e,0xbf653f31bf4ebeac,0x3ecf3f42bf223f6d,0x3efcbf7a3f80be79,0xbf58be893dc9bf7b,0x3d973f6fbf5c3f3e,0x3f80bea13ef13f35,0xbf1dbf133edbbf7d,
0xbf22bef13ec4bf80,0xbe953f7fbf7b3f0e,0xbdc93f75bf6d3f35,0x3f62bf463f553e48,0x3f46bf623f6d0000,0xbf753dc9be48bf55,0xbf7f3e95bec4bf35,0x3ef13f22bf0e3f7b,
0x3f46bf623f6d8000,0xbf753dc9be48bf55,0xbf7f3e95bec4bf35,0x3ef13f22bf0e3f7b,0x3f223ef1bec43f80,0x3e95bf7f3f7bbf0e,0x3dc9bf753f6dbf35,0xbf623f46bf55be48,
0x3eb83f27bf223f7b,0x3f1dbf7c3f7dbeac,0xbf7a3e89be95bf35,0x3ea13f31bf2c3f78,0xbf803ee6bef1bf0e,0x3efc3f09bf043f80,0x3f13bf7e3f7fbec4,0xbf7f3ecfbedbbf18,
0xbf6f3f42bf46be48,0x3f4a3e2fbe163f71,0x3e60bf773f75bf35,0xbf733f39bf3ebe79,0x3cc9bf653f62bf55,0xbf5f3f58bf5cbd49,0x3f513dfbbdc93f6d,0x3d97bf6a3f67bf4e,
0x3eacbf783f7bbf35,0xbf7d3f2cbf22be95,0xbf803f18bf0ebec4,0x3f043edbbef13f7f,0xbf673f5cbf550000,0x3f4e3d49bdc93f62,0x3f3e3e16be483f6d,0x3e79bf713f75bf46,
0x3f71be793e483f35,0xbe16bf3e3f46bf75,0xbd49bf4e3f55bf6d,0xbf5c3f67bf623dc9,0xbedbbf043f0ebf80,0xbf183f80bf7f3ef1,0xbf2c3f7dbf7b3ec4,0x3f78beac3e953f22,
0xbf7e3f39bf22be48,0x3f093ea1bedb3f78,0x3d97bf513f62bf6d,0xbf6f3f5fbf4e3d49,0x3f77becf3e953f0e,0xbe2fbf273f3ebf7d,0xbee63f7abf7f3f35,0x3f80bf1d3f043eac,
0xbdfbbf313f46bf7b,0xbf583f73bf673e79,0x3f7fbf133ef13ec4,0xbeb8befc3f18bf80,0xbe893f6abf753f55,0x3f7cbf423f2c3e16,0xbf653e60bdc9bf35,0xbcc93f4abf5c3f71,
0x3e483f0ebf353f80,0x3f55bf7b3f6dbec4,0x3f7bbf553f350000,0xbf0ebe483ec4bf6d,0xbe48bf0e3f35bf80,0xbf553f7bbf6d3ec4,0xbf7b3f55bf350000,0x3f0e3e48bec43f6d,
0xbf7b3f55bf358000,0x3f0e3e48bec43f6d,0x3e483f0ebf353f80,0x3f55bf7b3f6dbec4,0x3f7bbf553f358000,0xbf0ebe483ec4bf6d,0xbe48bf0e3f35bf80,0xbf553f7bbf6d3ec4,
0x3f4abf803f75bf0e,0xbf583ea1bd49bf18,0x3f42be2fbdc93f35,0x3eb8bf5f3f78bf67,0xbf773f6abf463e48,0x3f133d97beac3f5c,0xbee6be603ef1bf6d,0xbf313f7ebf7d3f2c,
0x3f1d3cc9be953f55,0x3f09bf733f80bf4e,0xbf273f7cbf7f3f35,0x3f6fbefc3e793edb,0xbe89becf3f22bf7b,0xbf513f7fbf713f04,0x3f65bf7a3f62bec4,0xbf393dfb3e16bf3e,
0xbf2c3e163e48bf35,0xbf043f67bf7f3f62,0xbf713f78bf553ec4,0x3f18bd49be953f46,0x3f80bf4e3f0e0000,0xbe79beac3f22bf75,0x3edbbf5c3f7bbf6d,0xbf7d3f3ebef1bdc9,
0x3f3ebf7d3f7bbf35,0xbf5c3edbbdc9bef1,0xbeacbe793f0ebf6d,0xbf4e3f80bf753f22,0xbd493f18bf553f80,0x3f78bf713f46be95,0x3f67bf043e483ec4,0x3e16bf2c3f62bf7f,
0xbf6a3f7fbf623f0e,0x3f1dbe2fbe793f2c,0xbf583efcbdc9bec4,0xbea13f39bf713f7d,0xbcc9bee63f46bf7b,0xbf773f7abf4e3edb,0x3f51bf7e3f75bf35,0xbf423eb83d49bf04,
0xbecfbd973ef1bf55,0xbf4a3f7cbf783f3e,0x3f09bf5f3f7fbf6d,0xbf733f31beacbe16,0x3f80bf653f22be48,0xbe89be603f18bf67,0x3f13bdfbbe953f35,0x3f27bf6f3f80bf5c,
0x3e95bf223f6dbf80,0xbf7f3f62bf0e3e48,0xbef13dc93ec4bf35,0xbf463f75bf7b3f55,0xbf753f46bec40000,0xbdc93ef1bf553f7b,0xbf623f7fbf6d3f35,0x3f22be95be483f0e,
0x3f75bf463ec48000,0x3dc9bef13f55bf7b,0x3f62bf7f3f6dbf35,0xbf223e953e48bf0e,0x3e95bf223f6dbf80,0xbf7f3f62bf0e3e48,0xbef13dc93ec4bf35,0xbf463f75bf7b3f55,
0xbf513f1dbdc9be48,0xbee63f31bf783f80,0xbeb83d973ef1bf35,0xbf5f3f7abf713f4e,0xbf583f77bf753f55,0x3f27becfbe163edb,0xbf803f73bf223ec4,0x3dfb3e2fbf2c3f5c,
0x3f13bf4a3f7fbf7b,0xbf653f39be79bd49,0x3f6fbf7f3f62bf35,0xbefc3e603eacbf18,0xbf093e893e95bf0e,0xbf423f6abf7d3f67,0x3cc9bea13f46bf6d,0xbf7e3f7cbf3e3f04,
0xbf783f80bf553f35,0x3eacbe16bef13f22,0xbf4e3f67bf7b3f6d,0x3f2cbf04bdc93e95,0xbf5c3f3ebe480000,0xbedb3f18bf753f7f,0xbf7d3f71bf0e3ec4,0xbd493e79bf463f62,
0xbe793d493f0ebf35,0xbf713f7dbf623f46,0xbf183edb3e48bec4,0xbf3e3f5cbf7f3f75,0x3f04bf2c3f7bbf80,0xbf673f4ebe953dc9,0x3e16beac3f55bf6d,0xbf803f78bf223ef1,
0xbf423f51bf7f3f7b,0x3f31bf1dbd493e16,0xbf5f3f6abf753f6d,0x3f09bee6be793eac,0xbf733f7abf623f55,0x3eb8be89bedb3f04,0xbf7e3f80bf463f35,0x3e2fbd97bf183f2c,
0xbf273f133dc9be48,0xbf393f4abf803f7d,0xbefc3ecf3e95bec4,0xbf583f65bf783f71,0xbea13e603ef1bf0e,0xbf6f3f77bf673f5c,0xbdfb3cc93f22bf35,0xbf7c3f7fbf4e3f3e,
};
__device__ __align__(1024) uint8_t g_hT[32 * 262144];
__device__ __align__(1024) bf16 g_U[128 * 2 * 8 * 1024];
__device__ __align__(16) uint2 g_gate[2048];
__device__ __align__(16) uint4 g_agg[8 * 1024];
__device__ unsigned g_cnt[8 * 32];
constexpr int CNT_U = 0, CNT_V = 1, CNT_H = 2  , CNT_DONE = 4, CNT_EPOCH = 5;
#define PROFK(i) do { } while (0)
#define PROFC(i) do { } while (0)
#define PROF(i) do { } while (0)

constexpr int STAGE_BYTES = 49152;
constexpr int OFF_W = 0;
constexpr int OFF_F = 32768;
constexpr int OFF_TW = 40960;
constexpr int OFF_HS = 49152;
constexpr int OFF_A2 = 32768, OFF_B2 = 114688;
constexpr int OFF_U = 4 * STAGE_BYTES;
constexpr int OFF_G = OFF_U + 32768;
constexpr int OFF_BAR = OFF_G + 1024;
constexpr int OFF_REL = OFF_BAR + 224;
constexpr int OFF_GS = OFF_BAR + 256;
constexpr int SMEM_BYTES = OFF_GS + 128;
constexpr int BAR_FULL = 0  , BAR_FULL2 = 4  , BAR_X = 9, BAR_HF = 10, BAR_U = 11, BAR_S0 = 12, BAR_H1 = 13, BAR_V = 14,
              BAR_CD = 15,
              BAR_G1 = 16, BAR_C = 17, BAR_R8 = 18, BAR_H = 19  , BAR_EMPTY2 = 23  , NBAR = 28;

#define DEVI __device__ __forceinline__
constexpr unsigned SPIN_LIMIT = 1u << 22;

DEVI uint32_t smem_u32(const void* p) { return (uint32_t)__cvta_generic_to_shared(p); }
DEVI uint64_t gtime() { uint64_t t; asm volatile("mov.u64 %0, %%globaltimer;" : "=l"(t)); return t; }
DEVI void mbar_init(uint32_t bar, uint32_t cnt) { asm volatile("mbarrier.init.shared::cta.b64 [%0], %1;" :: "r"(bar), "r"(cnt) : "memory"); }
DEVI void mbar_expect_tx(uint32_t bar, uint32_t bytes) { asm volatile("mbarrier.arrive.expect_tx.shared::cta.b64 _, [%0], %1;" :: "r"(bar), "r"(bytes) : "memory"); }
DEVI void mbar_arrive(uint32_t bar) { asm volatile("mbarrier.arrive.shared::cta.b64 _, [%0];" :: "r"(bar) : "memory"); }
DEVI void mbar_wait(uint32_t bar, uint32_t parity) {
    asm volatile("{\n.reg .pred p;\n.reg .u32 n;\nmov.u32 n, 0;\n"
                 "LW:\nmbarrier.try_wait.parity.shared::cta.b64 p, [%0], %1;\n@p bra LD;\n"
                 "add.u32 n, n, 1;\nsetp.lt.u32 p, n, %2;\n@p bra LW;\nLD:\n}"
                 :: "r"(bar), "r"(parity), "n"(1 << 17) : "memory");
}
DEVI bool elect() {
    uint32_t p;
    asm volatile("{\n.reg .pred P;\nelect.sync _|P, 0xffffffff;\nselp.u32 %0, 1, 0, P;\n}" : "=r"(p));
    return p;
}
DEVI void fence_barrier_init() { asm volatile("fence.mbarrier_init.release.cluster;" ::: "memory"); }
DEVI void fence_proxy_async_smem() { asm volatile("fence.proxy.async.shared::cta;" ::: "memory"); }
DEVI void helper_sync() { asm volatile("bar.sync 1, 128;" ::: "memory"); }

DEVI void wait_counter(const unsigned* p, unsigned target) {
    for (unsigned n = 0;; n++) {
        unsigned v;
        asm volatile("ld.acquire.gpu.global.u32 %0, [%1];" : "=r"(v) : "l"(p) : "memory");
        if ((int)(v - target) >= 0 || n > SPIN_LIMIT) break;
    }
}
DEVI void signal_counter(unsigned* p) {
    asm volatile("red.relaxed.gpu.global.add.u32 [%0], 1;" :: "l"(p) : "memory");
}

DEVI void tma_load_3d(uint32_t dst, const CUtensorMap* map, uint32_t bar, int c0, int c1, int c2) {
    asm volatile("cp.async.bulk.tensor.3d.shared::cluster.global.mbarrier::complete_tx::bytes [%0], [%1, {%3, %4, %5}], [%2];"
        :: "r"(dst), "l"(map), "r"(bar), "r"(c0), "r"(c1), "r"(c2) : "memory");
}
DEVI void tma_load_4d(uint32_t dst, const CUtensorMap* map, uint32_t bar, int c0, int c1, int c2, int c3) {
    asm volatile("cp.async.bulk.tensor.4d.shared::cluster.global.mbarrier::complete_tx::bytes [%0], [%1, {%3, %4, %5, %6}], [%2];"
        :: "r"(dst), "l"(map), "r"(bar), "r"(c0), "r"(c1), "r"(c2), "r"(c3) : "memory");
}
DEVI void tma_store_5d(const CUtensorMap* map, uint32_t src, int c0, int c4) {
    asm volatile("cp.async.bulk.tensor.5d.global.shared::cta.bulk_group [%0, {%2, %4, %4, %4, %3}], [%1];"
        :: "l"(map), "r"(src), "r"(c0), "r"(c4), "r"(0) : "memory");
}
DEVI void tma_store_4d(const CUtensorMap* map, uint32_t src, int c0, int c1, int c2, int c3) {
    asm volatile("cp.async.bulk.tensor.4d.global.shared::cta.bulk_group [%0, {%2, %3, %4, %5}], [%1];"
        :: "l"(map), "r"(src), "r"(c0), "r"(c1), "r"(c2), "r"(c3) : "memory");
}
DEVI void bulk_load(uint32_t dst, const void* src, uint32_t bytes, uint32_t bar) {
    asm volatile("cp.async.bulk.shared::cluster.global.mbarrier::complete_tx::bytes [%0], [%1], %2, [%3];"
        :: "r"(dst), "l"(src), "r"(bytes), "r"(bar) : "memory");
}
DEVI void bulk_prefetch_l2(const void* src, uint32_t bytes) {
    asm volatile("cp.async.bulk.prefetch.L2.global [%0], %1;" :: "l"(src), "r"(bytes) : "memory");
}
DEVI void bulk_store(void* dst, uint32_t src, uint32_t bytes) {
    asm volatile("cp.async.bulk.global.shared::cta.bulk_group [%0], [%1], %2;" :: "l"(dst), "r"(src), "r"(bytes) : "memory");
}
DEVI void bulk_commit() { asm volatile("cp.async.bulk.commit_group;" ::: "memory"); }
DEVI void bulk_wait0() { asm volatile("cp.async.bulk.wait_group 0;" ::: "memory"); }

DEVI void wgmma_fence() { asm volatile("wgmma.fence.sync.aligned;" ::: "memory"); }
DEVI void wgmma_commit() { asm volatile("wgmma.commit_group.sync.aligned;" ::: "memory"); }
template<int N> DEVI void wgmma_wait() { asm volatile("wgmma.wait_group.sync.aligned %0;" :: "n"(N) : "memory"); }
template<int N> DEVI void wgmma_wait_all(float (&d)[N]) {
    wgmma_wait<0>();
#pragma unroll
    for (int i = 0; i < N; i++) asm volatile("" : "+f"(d[i]) :: "memory");
}
template<int R> DEVI void reg_alloc() { asm volatile("setmaxnreg.inc.sync.aligned.u32 %0;" :: "n"(R)); }
template<int R> DEVI void reg_dealloc() { asm volatile("setmaxnreg.dec.sync.aligned.u32 %0;" :: "n"(R)); }

DEVI uint64_t make_desc(uint32_t addr, uint32_t lbo, uint32_t sbo, uint32_t mode = 1) {
    return (uint64_t)(((addr & 0x3FFFF) >> 4) | ((lbo >> 4) << 16)) | ((uint64_t)((sbo >> 4) | (mode << 30)) << 32);
}

#define ACC8(a, o) "+f"(a[o+0]), "+f"(a[o+1]), "+f"(a[o+2]), "+f"(a[o+3]), "+f"(a[o+4]), "+f"(a[o+5]), "+f"(a[o+6]), "+f"(a[o+7])
#define ACC32(a, o) ACC8(a, o), ACC8(a, o+8), ACC8(a, o+16), ACC8(a, o+24)

DEVI void wgmma_n256(float (&d)[128], uint64_t da, uint64_t db, int scale_d) {
    asm volatile("{\n.reg .pred p;\nsetp.ne.b32 p, %130, 0;\n"
        "wgmma.mma_async.sync.aligned.m64n256k16.f32.bf16.bf16 "
        "{%0, %1, %2, %3, %4, %5, %6, %7, %8, %9, %10, %11, %12, %13, %14, %15, "
        "%16, %17, %18, %19, %20, %21, %22, %23, %24, %25, %26, %27, %28, %29, %30, %31, "
        "%32, %33, %34, %35, %36, %37, %38, %39, %40, %41, %42, %43, %44, %45, %46, %47, "
        "%48, %49, %50, %51, %52, %53, %54, %55, %56, %57, %58, %59, %60, %61, %62, %63, "
        "%64, %65, %66, %67, %68, %69, %70, %71, %72, %73, %74, %75, %76, %77, %78, %79, "
        "%80, %81, %82, %83, %84, %85, %86, %87, %88, %89, %90, %91, %92, %93, %94, %95, "
        "%96, %97, %98, %99, %100, %101, %102, %103, %104, %105, %106, %107, %108, %109, %110, %111, "
        "%112, %113, %114, %115, %116, %117, %118, %119, %120, %121, %122, %123, %124, %125, %126, %127}, "
        "%128, %129, p, 1, 1, 0, 0;\n}\n"
        : ACC32(d, 0), ACC32(d, 32), ACC32(d, 64), ACC32(d, 96)
        : "l"(da), "l"(db), "r"(scale_d));
}
template<int TB>
DEVI void wgmma_n128(float (&d)[64], uint64_t da, uint64_t db, int scale_d) {
    asm volatile("{\n.reg .pred p;\nsetp.ne.b32 p, %66, 0;\n"
        "wgmma.mma_async.sync.aligned.m64n128k16.f32.bf16.bf16 "
        "{%0, %1, %2, %3, %4, %5, %6, %7, %8, %9, %10, %11, %12, %13, %14, %15, "
        "%16, %17, %18, %19, %20, %21, %22, %23, %24, %25, %26, %27, %28, %29, %30, %31, "
        "%32, %33, %34, %35, %36, %37, %38, %39, %40, %41, %42, %43, %44, %45, %46, %47, "
        "%48, %49, %50, %51, %52, %53, %54, %55, %56, %57, %58, %59, %60, %61, %62, %63}, "
        "%64, %65, p, 1, 1, 1, %67;\n}\n"
        : ACC32(d, 0), ACC32(d, 32)
        : "l"(da), "l"(db), "r"(scale_d), "n"(TB));
}
template<int SCALE_D>
DEVI void wgmma_rs_n128(float (&d)[64], const uint4& a, uint64_t db) {
    asm volatile("{\n.reg .pred p;\nsetp.ne.b32 p, %69, 0;\n"
        "wgmma.mma_async.sync.aligned.m64n128k16.f32.bf16.bf16 "
        "{%0, %1, %2, %3, %4, %5, %6, %7, %8, %9, %10, %11, %12, %13, %14, %15, "
        "%16, %17, %18, %19, %20, %21, %22, %23, %24, %25, %26, %27, %28, %29, %30, %31, "
        "%32, %33, %34, %35, %36, %37, %38, %39, %40, %41, %42, %43, %44, %45, %46, %47, "
        "%48, %49, %50, %51, %52, %53, %54, %55, %56, %57, %58, %59, %60, %61, %62, %63}, "
        "{%64, %65, %66, %67}, %68, p, 1, 1, 1;\n}\n"
        : ACC32(d, 0), ACC32(d, 32)
        : "r"(a.x), "r"(a.y), "r"(a.z), "r"(a.w), "l"(db), "n"(SCALE_D));
}
DEVI void wgmma_n16(float (&d)[8], uint64_t da, uint64_t db) {
    asm volatile("{\n.reg .pred p;\nsetp.ne.b32 p, 0, 0;\n"
        "wgmma.mma_async.sync.aligned.m64n16k16.f32.bf16.bf16 "
        "{%0, %1, %2, %3, %4, %5, %6, %7}, %8, %9, p, 1, 1, 1, 0;\n}\n"
        : ACC8(d, 0)
        : "l"(da), "l"(db));
}
template<int SCALE_D>
DEVI void wgmma_rs_n64(float (&d)[32], const uint32_t (&a)[4], uint64_t db) {
    asm volatile("{\n.reg .pred p;\nsetp.ne.b32 p, %37, 0;\n"
        "wgmma.mma_async.sync.aligned.m64n64k16.f32.bf16.bf16 "
        "{%0, %1, %2, %3, %4, %5, %6, %7, %8, %9, %10, %11, %12, %13, %14, %15, "
        "%16, %17, %18, %19, %20, %21, %22, %23, %24, %25, %26, %27, %28, %29, %30, %31}, "
        "{%32, %33, %34, %35}, %36, p, 1, 1, 0;\n}\n"
        : ACC32(d, 0)
        : "r"(a[0]), "r"(a[1]), "r"(a[2]), "r"(a[3]), "l"(db), "n"(SCALE_D));
}
DEVI void ldsm_x4_t(uint32_t (&r)[4], uint32_t addr) {
    asm volatile("ldmatrix.sync.aligned.m8n8.x4.trans.shared.b16 {%0, %1, %2, %3}, [%4];"
        : "=r"(r[0]), "=r"(r[1]), "=r"(r[2]), "=r"(r[3]) : "r"(addr) : "memory");
}
DEVI void ldsm_x4(uint32_t (&r)[4], uint32_t addr) {
    asm volatile("ldmatrix.sync.aligned.m8n8.x4.shared.b16 {%0, %1, %2, %3}, [%4];"
        : "=r"(r[0]), "=r"(r[1]), "=r"(r[2]), "=r"(r[3]) : "r"(addr) : "memory");
}
DEVI void stsm_x4(uint32_t addr, uint32_t r0, uint32_t r1, uint32_t r2, uint32_t r3) {
    asm volatile("stmatrix.sync.aligned.m8n8.x4.shared.b16 [%0], {%1, %2, %3, %4};"
        :: "r"(addr), "r"(r0), "r"(r1), "r"(r2), "r"(r3) : "memory");
}
DEVI void stsm_x4_t(uint32_t addr, uint32_t r0, uint32_t r1, uint32_t r2, uint32_t r3) {
    asm volatile("stmatrix.sync.aligned.m8n8.x4.trans.shared.b16 [%0], {%1, %2, %3, %4};"
        :: "r"(addr), "r"(r0), "r"(r1), "r"(r2), "r"(r3) : "memory");
}
DEVI uint32_t movm(uint32_t a) { uint32_t d; asm volatile("movmatrix.sync.aligned.m8n8.trans.b16 %0, %1;" : "=r"(d) : "r"(a)); return d; }
DEVI uint32_t pack2(float lo, float hi) { uint32_t d; asm("cvt.rn.bf16x2.f32 %0, %1, %2;" : "=r"(d) : "f"(hi), "f"(lo)); return d; }
DEVI float bf_lo(uint32_t v) { return __uint_as_float(v << 16); }
DEVI float bf_hi(uint32_t v) { return __uint_as_float(v & 0xffff0000u); }
DEVI float bf_round(float v) { return __bfloat162float(__float2bfloat16_rn(v)); }
DEVI uint32_t bf_mul2(uint32_t a, uint32_t b) { uint32_t d; asm("mul.rn.bf16x2 %0, %1, %2;" : "=r"(d) : "r"(a), "r"(b)); return d; }
DEVI uint4 lds128u(uint32_t a) { uint4 v; asm volatile("ld.shared.v4.u32 {%0, %1, %2, %3}, [%4];" : "=r"(v.x), "=r"(v.y), "=r"(v.z), "=r"(v.w) : "r"(a) : "memory"); return v; }
DEVI void sts128u(uint32_t a, uint32_t x, uint32_t y, uint32_t z, uint32_t w) { asm volatile("st.shared.v4.u32 [%0], {%1, %2, %3, %4};" :: "r"(a), "r"(x), "r"(y), "r"(z), "r"(w) : "memory"); }
DEVI uint2 lds64u(uint32_t a) { uint2 v; asm volatile("ld.shared.v2.u32 {%0, %1}, [%2];" : "=r"(v.x), "=r"(v.y) : "r"(a) : "memory"); return v; }
DEVI uint32_t ldg32u(const void* p) { uint32_t v; asm volatile("ld.global.nc.u32 %0, [%1];" : "=r"(v) : "l"(p) : "memory"); return v; }
DEVI void sts64(uint32_t a, float x, float y) { asm volatile("st.shared.v2.f32 [%0], {%1, %2};" :: "r"(a), "f"(x), "f"(y) : "memory"); }
DEVI uint32_t ldg16(const bf16* p) { uint32_t v; asm volatile("ld.global.nc.u16 %0, [%1];" : "=r"(v) : "l"(p)); return v; }
DEVI void sts32(uint32_t a, uint32_t v) { asm volatile("st.shared.u32 [%0], %1;" :: "r"(a), "r"(v) : "memory"); }
DEVI void cmul2(uint32_t& x, uint32_t& y, uint32_t c, uint32_t s) {
    asm("{\n.reg .b32 t, u;\nmul.rn.bf16x2 t, %1, %3;\nneg.bf16x2 t, t;\nmul.rn.bf16x2 u, %1, %2;\n"
        "fma.rn.bf16x2 %1, %0, %3, u;\nfma.rn.bf16x2 %0, %0, %2, t;\n}" : "+r"(x), "+r"(y) : "r"(c), "r"(s));
}
DEVI void sts16(uint32_t a, float v) { asm volatile("st.shared.u16 [%0], %1;" :: "r"(a), "r"(pack2(v, v)) : "memory"); }

DEVI float2 cmul(float2 a, float2 b) { return make_float2(fmaf(a.x, b.x, -a.y * b.y), fmaf(a.x, b.y, a.y * b.x)); }
DEVI float2 cfma(float2 a, float2 b, float2 c) { return make_float2(fmaf(a.x, b.x, fmaf(-a.y, b.y, c.x)), fmaf(a.x, b.y, fmaf(a.y, b.x, c.y))); }
DEVI float2 cadd(float2 a, float2 b) { return make_float2(a.x + b.x, a.y + b.y); }
DEVI float2 csub(float2 a, float2 b) { return make_float2(a.x - b.x, a.y - b.y); }
DEVI void fft4(float2& a, float2& b, float2& c, float2& d) {
    const float2 s0 = cadd(a, c), s1 = csub(a, c), s2 = cadd(b, d), t = csub(b, d), s3 = make_float2(t.y, -t.x);
    a = cadd(s0, s2); b = cadd(s1, s3); c = csub(s0, s2); d = csub(s1, s3);
}

struct Params {
    const bf16 *lam_re, *lam_im, *log_dt, *dskip, *gate_w, *c_re, *c_im, *w_r, *w_i;
    int swapB;
    uint8_t perm[68];
};

DEVI void pace(uint32_t cnt_addr) {
    uint32_t v0, v;
    asm volatile("ld.volatile.shared.u32 %0, [%1];" : "=r"(v0) : "r"(cnt_addr) : "memory");
    const unsigned t0 = clock();
    do {
        __nanosleep(20);
        asm volatile("ld.volatile.shared.u32 %0, [%1];" : "=r"(v) : "r"(cnt_addr) : "memory");
    } while (v == v0 && clock() - t0 < 1300u);
}

DEVI void radix8(uint32_t sb, uint32_t gtab, int hf, int w, int lane, int bar) {
    const uint64_t dg = make_desc(gtab, 128, 256, 0);
    const uint32_t st = sb + OFF_U + hf * 8192 + (lane >> 4) * 16384 + (lane & 7) * 128 + (((2 * w + ((lane >> 3) & 1)) ^ (lane & 7)) << 4);
    float acc[8][8];
    const uint64_t da = make_desc(sb + OFF_U + hf * 8192, 16, 16384);
    wgmma_fence();
#pragma unroll
    for (int i = 0; i < 8; i++) wgmma_n16(acc[i], da + 64 * i, dg);
    wgmma_commit();
    wgmma_wait<0>();
    asm volatile("bar.sync %0, 128;" :: "r"(bar) : "memory");
#pragma unroll
    for (int i = 0; i < 8; i++)
        stsm_x4_t((st ^ ((i & 3) << 4)) + i * 1024,
                  pack2(acc[i][0], acc[i][1]), pack2(acc[i][2], acc[i][3]), pack2(acc[i][4], acc[i][5]), pack2(acc[i][6], acc[i][7]));
}

template<int N> DEVI void c_take(float (&acc)[32], uint32_t (&p)[16]) {
    wgmma_wait<N>();
#pragma unroll
    for (int i = 0; i < 32; i++) asm volatile("" : "+f"(acc[i]) :: "memory");
#pragma unroll
    for (int i = 0; i < 16; i++) p[i] = pack2(acc[2 * i], acc[2 * i + 1]);
}
DEVI void c_mm4(float (&acc)[32], const uint32_t (&a)[4][4], uint64_t df) {
    wgmma_fence();
    wgmma_rs_n64<0>(acc, a[0], df);
    wgmma_rs_n64<1>(acc, a[1], df + 2);
    wgmma_rs_n64<1>(acc, a[2], df + 4);
    wgmma_rs_n64<1>(acc, a[3], df + 6);
    wgmma_commit();
}
template<int H> DEVI void c_mm2(float (&acc)[32], const uint32_t (&a)[2][4], uint64_t df) {
    wgmma_fence();
    wgmma_rs_n64<H>(acc, a[0], df + 2 * H);
    wgmma_rs_n64<1>(acc, a[1], df + 2 * H + 4);
    wgmma_commit();
}
DEVI void c_twiddle(uint32_t (&p)[16], uint32_t (&a)[2][2][4], uint32_t tw) {
#pragma unroll
    for (int hh = 0; hh < 2; hh++)
#pragma unroll
        for (int jp = 0; jp < 2; jp++) {
            const uint4 w = lds128u(tw + (hh * 2 + jp) * 512);
#pragma unroll
            for (int jl = 0; jl < 2; jl++) {
                const int o = 4 * jp + 2 * jl + hh;
                cmul2(p[o], p[8 + o], jl ? w.z : w.x, jl ? w.w : w.y);
                a[jp][0][2 * hh + jl] = movm(p[o]);
                a[jp][1][2 * hh + jl] = movm(p[8 + o]);
            }
        }
}
DEVI void c_stage(float (&acc)[2][32], uint32_t tw, uint64_t df) {
    uint32_t p[16], a0[2][2][4], a1[2][2][4];
    c_take<1>(acc[0], p);
    c_twiddle(p, a0, tw);
    c_mm2<0>(acc[0], a0[0], df);
    c_take<1>(acc[1], p);
    c_mm2<0>(acc[1], a0[1], df);
    c_twiddle(p, a1, tw + 2048);
    c_mm2<1>(acc[0], a1[0], df);
    c_mm2<1>(acc[1], a1[1], df);
}

DEVI void phase_c(uint32_t sb, int warp, int lane) {
    PROFC(0);
    const uint64_t df = make_desc(sb + OFF_F, 16, 1024);
    const uint32_t tw = sb + OFF_TW + lane * 16;
    float acc[2][32];
    const uint32_t xa = sb + OFF_U + ((lane >> 4) * 4 + ((lane & 7) >> 1)) * 1024 + warp * 128
                      + ((((lane & 1) * 4 + ((lane >> 3) & 1)) ^ warp ^ ((lane >> 1) & 3)) << 4);
#pragma unroll
    for (int h = 0; h < 2; h++) {
        uint32_t a[4][4];
#pragma unroll
        for (int s = 0; s < 4; s++) ldsm_x4_t(a[s], (xa ^ (h * 32)) + (s & 1) * 8192 + (s >> 1) * 16384);
        c_mm4(acc[h], a, df);
    }
    PROFC(1);
    c_stage(acc, tw, df);
    PROFC(2);
    const uint32_t wa = sb + OFF_W + warp * 4096 + (lane >> 4) * 2048 + (lane & 7) * 64 + ((((lane >> 3) & 1) ^ ((lane >> 1) & 3)) << 4);
#pragma unroll
    for (int h = 0; h < 2; h++) {
        uint32_t p[16], a[4][4];
        c_take<1>(acc[h], p);
#pragma unroll
        for (int j = 0; j < 4; j++) {
            uint32_t w[4];
            ldsm_x4_t(w, (wa ^ (h * 32)) + j * 512);
#pragma unroll
            for (int hh = 0; hh < 2; hh++) {
                cmul2(p[2 * j + hh], p[8 + 2 * j + hh], w[hh], w[2 + hh]);
                a[j >> 1][2 * (j & 1) + hh] = p[8 + 2 * j + hh];
                a[2 + (j >> 1)][2 * (j & 1) + hh] = p[2 * j + hh];
            }
        }
        c_mm4(acc[h], a, df);
    }
    PROFC(3);
    c_stage(acc, tw, df);
    PROFC(4);
#pragma unroll
    for (int h = 0; h < 2; h++) {
        uint32_t p[16];
        if (h) c_take<0>(acc[1], p); else c_take<1>(acc[0], p);
#pragma unroll
        for (int s = 0; s < 4; s++)
            stsm_x4_t((xa ^ (h * 32)) + (s & 1) * 8192 + ((s >> 1) ^ 1) * 16384, p[4 * s], p[4 * s + 1], p[4 * s + 2], p[4 * s + 3]);
    }
    PROFC(5);
}

#define PFW0 4
#define PACE_H 200
#define PACE_V 300
#define PFC0 8
__global__ void __cluster_dims__(2, 1, 1) __launch_bounds__(384, 1)
fused_kernel(const __grid_constant__ CUtensorMap mapB, const __grid_constant__ CUtensorMap mapX,
             const __grid_constant__ CUtensorMap mapXs, const __grid_constant__ CUtensorMap mapU0,
             const __grid_constant__ CUtensorMap mapU2, const __grid_constant__ CUtensorMap mapXe,
             const __grid_constant__ CUtensorMap mapCre, const __grid_constant__ CUtensorMap mapCim,
             const __grid_constant__ CUtensorMap mapV, const __grid_constant__ CUtensorMap mapO,
             const __grid_constant__ Params P) {
    extern __shared__ __align__(1024) uint8_t sm[];
    const uint32_t sb = smem_u32(sm);
    const uint32_t bars = sb + OFF_BAR, prog = sb + OFF_REL + 20;
    const int b = P.perm[blockIdx.x >> 1] * 2 + (blockIdx.x & 1), tid = threadIdx.x, warp = __shfl_sync(0xffffffffu, tid >> 5, 0), lane = tid & 31;
    const bool main_cta = b < 128;
    if (b == 129) return;
    const int b2 = ((b & 6) + ((b >> 4) & 1)) * 16 + (b & 8) + (b >> 5) * 2 + (b & 1);

    const int cls = b == 128 ? 128 : (b & 31) ? (b & 31) + 64 * (b >> 5) : (b == 64 ? 32 : b == 32 ? 64 : b);
    auto load_g1 = [&](int it) {
        const uint32_t full = bars + 8 * (BAR_FULL + (it & 3)), st = sb + (it & 3) * STAGE_BYTES;
        mbar_expect_tx(full, STAGE_BYTES);
        tma_load_4d(st, &mapB, full, it * 64, 0, 0, (b & 15) * 8);
        tma_load_4d(st + 16384, &mapX, full, it * 64, 0, 0, (b >> 4) * 128);
    };
    auto load_c = [&](int k, int s) {
        const uint32_t full = bars + 8 * (BAR_FULL2 + s);
        mbar_expect_tx(full, 32768);
        tma_load_3d(sb + OFF_B2 + s * 16384, &mapCre + (k >> 4), full, 0, k < 32 ? (b2 & 14) * 64 : (k & 15) * 64, k < 32 ? k & 15 : b2 & ~1);
    };
    auto load_h = [&](int k, int s) {
        const uint8_t* src = k < 32 ? g_hT + (k * 8 + (b2 >> 4)) * 32768 : (const uint8_t*)c_inv + (k - 32) * 32768;
        bulk_load(sb + OFF_A2 + s * 16384, src + (b & 1) * 16384, 16384, bars + 8 * (BAR_FULL2 + s));
    };
    if (elect()) {
        if (warp < 10) asm volatile("prefetch.tensormap [%0];" :: "l"(&mapB + warp) : "memory");
        if (warp == 8) {
            PROF(0);
#pragma unroll
            for (int i = 0; i < NBAR; i++) mbar_init(bars + 8 * i, i < BAR_G1 ? 1 : i == BAR_G1 ? 2 : i == BAR_C ? 129 : 8);
            *(uint4*)(sm + OFF_REL) = make_uint4(0, 0, 0, 0);
            *(uint2*)(sm + OFF_REL + 16) = make_uint2(0, 0);
            fence_barrier_init();
            fence_proxy_async_smem();
            if (main_cta) {
#pragma unroll 1
                for (int it = 0; it < 4; it++) load_g1(it);
            }
            PROF(27);
        }
    }
    __syncthreads();
    auto load_epoch = [&]() {
        unsigned e;
        asm volatile("ld.volatile.global.u32 %0, [%1];" : "=r"(e) : "l"(&g_cnt[CNT_EPOCH * 32]));
        return e + 1;
    };
    const int g = lane >> 2, q = lane & 3;

    if (warp < 8) {
        reg_alloc<192>();
        if (tid == 0) PROF(28);
        const int wg = warp >> 2;
        unsigned epoch = 0;
        auto release = [&](int s) -> bool {
            if (warp & 3) return false;
            unsigned old = 0;
            if (elect()) asm volatile("atom.relaxed.cta.shared.inc.u32 %0, [%1], 1;" : "=r"(old) : "r"(sb + OFF_REL + 4 * s) : "memory");
            return __any_sync(0xffffffffu, old == 1);
        };
        if (main_cta) {
            float acc[128];
            const int tc = b >> 4;
            const int pp = (b & 15) * 64 + (tid >> 2);
            const bf16 lr_ = P.lam_re[pp], li_ = P.lam_im[pp], ld_ = P.log_dt[pp];
            const int gn = 16 * (b & 15) + 2 * warp + (lane >> 4);
            const uint32_t goff = 16384 + gn * 128 + ((((lane & 15) >> 1) ^ (gn & 7)) << 4) + (lane & 1) * 8;
            const uint2* gwp = (const uint2*)P.gate_w + (lane & 15);
            uint2 gw = __ldg(gwp);
            float gs = 0.f;
#pragma unroll 1
            for (int it = 0; it < 16; it++) {
                const int sg = it & 3;
                mbar_wait(bars + 8 * (BAR_FULL + sg), (it >> 2) & 1);
                if (tid == 0) PROFK(it);
                const uint32_t st = sb + sg * STAGE_BYTES;
                const uint64_t da = make_desc(st + wg * 8192, 16, 1024), db = make_desc(st + 16384, 16, 1024);
                uint2 xv = lds64u(st + goff);
                wgmma_fence();
#pragma unroll
                for (int j = 0; j < 4; j++) wgmma_n256(acc, da + 2 * j, db + 2 * j, (it | j) != 0);
                wgmma_commit();
                xv.x = bf_mul2(xv.x, gw.x); xv.y = bf_mul2(xv.y, gw.y);
                gs += (bf_lo(xv.x) + bf_hi(xv.x)) + (bf_lo(xv.y) + bf_hi(xv.y));
                gw = __ldg(gwp + ((it + 1) & 15) * 16);
                wgmma_wait<1>();
                if (it > 0 && it < 14 && release((it - 1) & 3) && elect()) {
                    if (it == 13) mbar_arrive(bars + 8 * BAR_S0);
                    else load_g1(it + 3);
                    asm volatile("st.volatile.shared.u32 [%0], %1;" :: "r"(prog), "r"(it) : "memory");
                }
                if (warp == 1 && elect()) {
                    if ((unsigned)(it - PFW0) < 4) bulk_prefetch_l2(((it & 1) ? P.w_i : P.w_r) + (size_t)(2 * b + (((it - PFW0) >> 1) & 1)) * 4104, 8208);
                    if ((unsigned)(it - PFC0) < 8) bulk_prefetch_l2(((b & 1) ? P.c_im : P.c_re) + (size_t)(b >> 1) * 16384 + (it - PFC0) * 2048, 4096);
                }
                __syncwarp();
            }
            epoch = load_epoch();
            float2 lam1, lam8, lam64, lam128, wq, w4, l64q;
            float m00, m01, m10, m11, sg2;
            {
                const float lr = __bfloat162float(lr_), li = __bfloat162float(li_);
                const float dt = bf_round(expf(__bfloat162float(ld_)));
                const float mag = expf(dt * lr);
                float sn, cs; sincospif(dt * li * 0.31830988618379067f, &sn, &cs);
                lam1 = make_float2(mag * cs, mag * sn);
                const float inv = 1.f / (lr * lr + li * li);
                const float2 coef = cmul(make_float2(lam1.x - 1.f, lam1.y), make_float2(lr * inv, -li * inv));
                m00 = coef.x; m01 = -coef.y; m10 = -coef.y; m11 = -coef.x; sg2 = -1.f;
                if (P.swapB) { lam1.y = -lam1.y; m00 = -coef.y; m01 = coef.x; m10 = -coef.x; m11 = -coef.y; sg2 = 1.f; }
                float2 z = cmul(lam1, lam1);
                z = cmul(z, z); lam8 = cmul(z, z);
                z = cmul(lam8, lam8); z = cmul(z, z);
                lam64 = cmul(z, z); lam128 = cmul(lam64, lam64);
                const float2 l256 = cmul(lam128, lam128), l512 = cmul(l256, l256);
                w4 = cmul(l512, l512);
                const float2 one = make_float2(1.f, 0.f);
                wq = cmul((q & 1) ? l256 : one, (q & 2) ? l512 : one);
                l64q = cmul((q & 1) ? lam64 : one, (q & 2) ? lam128 : one);
            }
#pragma unroll
            for (int o = 1; o < 16; o <<= 1) gs += __shfl_xor_sync(0xffffffffu, gs, o);
            {
                const float gg = bf_round(__fdividef(1.f, 1.f + __expf(-bf_round(gs))));
                if ((lane & 15) == 0) *(uint2*)(sm + OFF_GS + (2 * warp + (lane >> 4)) * 8) = make_uint2(__float_as_uint(gg), __float_as_uint(2.f * bf_round(1.f - gg)));
            }
            wgmma_wait_all(acc);
            if ((tid & 127) == 0) mbar_arrive(bars + 8 * BAR_G1);
            if (tid == 0) PROF(3);
            float2 ag[8];
#pragma unroll
            for (int c = 0; c < 8; c++) ag[c] = make_float2(acc[16 * c], acc[16 * c + 2]);
#pragma unroll
            for (int r = 1; r < 8; r++)
#pragma unroll
                for (int c = 0; c < 8; c++) {
                    const int i = 16 * c + 4 * (r >> 1) + (r & 1);
                    ag[c] = cfma(lam1, ag[c], make_float2(acc[i], acc[i + 2]));
                }
            float2 v = ag[0];
#pragma unroll
            for (int c = 1; c < 8; c++) v = cfma(lam8, v, ag[c]);
            {
                float2 n = make_float2(__shfl_up_sync(0xffffffffu, v.x, 1, 4), __shfl_up_sync(0xffffffffu, v.y, 1, 4));
                if (q >= 1) v = cfma(lam64, n, v);
                n = make_float2(__shfl_up_sync(0xffffffffu, v.x, 2, 4), __shfl_up_sync(0xffffffffu, v.y, 2, 4));
                if (q >= 2) v = cfma(lam128, n, v);
            }
            if (q == 3 && tc < 7) {
                asm volatile("st.volatile.global.v4.u32 [%0], {%1, %2, %3, %4};"
                    :: "l"(&g_agg[tc * 1024 + pp]), "r"(__float_as_uint(v.x)), "r"(epoch), "r"(__float_as_uint(v.y)), "r"(epoch) : "memory");
            }
            float2 ex = make_float2(__shfl_up_sync(0xffffffffu, v.x, 1, 4), __shfl_up_sync(0xffffffffu, v.y, 1, 4));
            if (q == 0) ex = make_float2(0.f, 0.f);
            {
                uint32_t z;
                asm volatile("ld.volatile.shared.u32 %0, [%1];" : "=r"(z) : "r"(prog) : "memory");
                z >>= 16;
                m00 = __uint_as_float(__float_as_uint(m00) | z); m01 = __uint_as_float(__float_as_uint(m01) | z);
                m10 = __uint_as_float(__float_as_uint(m10) | z); m11 = __uint_as_float(__float_as_uint(m11) | z);
            }
            auto scale = [&](float& x, float& y) { const float u = fmaf(m00, x, m01 * y); y = fmaf(m10, x, m11 * y); x = u; };
#pragma unroll
            for (int i = 0; i < 128; i += 4) { scale(acc[i], acc[i + 2]); scale(acc[i + 1], acc[i + 3]); }
#pragma unroll
            for (int c = 0; c < 7; c++) scale(ag[c].x, ag[c].y);
            {
                float2 part = make_float2(0.f, 0.f);
                const int c0 = tc - 1 - q, c1 = tc - 5 - q;
                if (c0 >= 0) {
                    uint4 r0, r1 = make_uint4(0, epoch, 0, epoch);
                    for (unsigned n = 0;; n++) {
                        asm volatile("ld.volatile.global.v4.u32 {%0, %1, %2, %3}, [%4];" : "=r"(r0.x), "=r"(r0.y), "=r"(r0.z), "=r"(r0.w) : "l"(&g_agg[c0 * 1024 + pp]) : "memory");
                        if (c1 >= 0) asm volatile("ld.volatile.global.v4.u32 {%0, %1, %2, %3}, [%4];" : "=r"(r1.x), "=r"(r1.y), "=r"(r1.z), "=r"(r1.w) : "l"(&g_agg[c1 * 1024 + pp]) : "memory");
                        if ((r0.y == epoch && r0.w == epoch && r1.y == epoch && r1.w == epoch) || n > SPIN_LIMIT) break;
                    }
                    part = cfma(w4, make_float2(__uint_as_float(r1.x), __uint_as_float(r1.z)), make_float2(__uint_as_float(r0.x), __uint_as_float(r0.z)));
                    part = cmul(wq, part);
                }
                __syncwarp();
                part.x += __shfl_xor_sync(0xffffffffu, part.x, 1); part.y += __shfl_xor_sync(0xffffffffu, part.y, 1);
                part.x += __shfl_xor_sync(0xffffffffu, part.x, 2); part.y += __shfl_xor_sync(0xffffffffu, part.y, 2);
                ex = cfma(l64q, part, ex);
            }
            if (tid == 0) PROF(4);
            scale(ex.x, ex.y);
            lam1.y *= sg2; lam8.y *= sg2;
#pragma unroll
            for (int c = 0; c < 8; c++) { const float2 n = cfma(lam8, ex, ag[c]); ag[c] = ex; ex = n; }
            mbar_wait(bars + 8 * BAR_G1, 0);
#pragma unroll
            for (int r = 0; r < 8; r++) {
#pragma unroll
                for (int c = 0; c < 8; c++) {
                    const int i = 16 * c + 4 * (r >> 1) + (r & 1);
                    ag[c] = cfma(lam1, ag[c], make_float2(acc[i], acc[i + 2]));
                }
                const uint32_t hs = sb + OFF_HS + ((tid * 16) ^ ((tid << 1) & 48)) + r * 4096;
                sts128u(hs + 32768, pack2(ag[0].x, ag[4].x), pack2(ag[1].x, ag[5].x), pack2(ag[2].x, ag[6].x), pack2(ag[3].x, ag[7].x));
                sts128u(hs, pack2(ag[0].y, ag[4].y), pack2(ag[1].y, ag[5].y), pack2(ag[2].y, ag[6].y), pack2(ag[3].y, ag[7].y));
                if (r & 1) {
                    fence_proxy_async_smem();
                    __syncwarp();
                    if (lane == 0) mbar_arrive(bars + 8 * (BAR_H + (r >> 1)));
                }
            }
            if (tid == 0) PROF(5);
        }
        mbar_wait(bars + 8 * BAR_C, 0);
        if (tid == 0) PROF(6);
        phase_c(sb, warp, lane);
        fence_proxy_async_smem();
        asm volatile("bar.sync 2, 256;" ::: "memory");
        if (tid == 0) mbar_arrive(bars + 8 * BAR_CD);
        if (tid == 0) PROF(7);
        radix8(sb, sb + OFF_G + 512, wg, warp & 3, lane, 5 + wg);
        fence_proxy_async_smem();
        __syncwarp();
        if (lane == 0) mbar_arrive(bars + 8 * BAR_R8);
        if (tid == 0) PROF(24);
        PROFC(6);
        if (main_cta) {
            float acc[64], acc2[64];
            uint32_t dk[16];
#pragma unroll
            for (int j = 0; j < 16; j++) dk[j] = ldg32u(P.dskip + (b2 & 14) * 64 + 2 * q + 8 * j);
            const int trow = 64 * (16 * (b & 1) + 2 * warp) + 32 * (g & 1) + 8 * (g >> 1) + (b2 >> 4);
            mbar_wait(bars + 8 * (BAR_FULL2 + 3), 0);
            if (tid == 0) PROF(16);
            const float2* gp = (const float2*)&g_gate[(trow & ~255) + ((trow & 62) << 2) + ((trow >> 5) & 6) + (trow & 1)];
            const float2 g0 = __ldcg(gp), g1 = __ldcg(gp + 2);
            int s = 3, sp = 0; uint32_t ph = 0;
#pragma unroll 1
            for (int k = 0; k < 32; k++) {
                mbar_wait(bars + 8 * (BAR_FULL2 + s), ph);
                if (tid == 0 && (k & 1) == 0) PROFK(16 + (k >> 1));
                const uint64_t da = make_desc(sb + OFF_A2 + s * 16384 + wg * 8192, 4096, 512, 2), db = make_desc(sb + OFF_B2 + s * 16384, 16, 1024);
                wgmma_fence();
#pragma unroll
                for (int j = 0; j < 4; j++) wgmma_n128<0>(acc, da + 64 * j, db + 2 * j, (k | j) != 0);
                wgmma_commit();
                wgmma_wait<1>();
                if (k > 0 && lane == 0) mbar_arrive(bars + 8 * (BAR_EMPTY2 + sp));
                __syncwarp();
                sp = s;
                if (s == 2) ph ^= 1;
                if (++s == 5) s = 0;
            }
            if (wg) asm volatile("bar.sync 3, 256;" ::: "memory");
#pragma unroll
            for (int k = 0; k < 4; k++) {
                const int s = k;
                mbar_wait(bars + 8 * (BAR_FULL2 + s), k == 3);
                const uint64_t da = make_desc(sb + OFF_A2 + s * 16384 + wg * 8192, 4096, 512, 2), db = make_desc(sb + OFF_B2 + s * 16384, 8192, 1024);
                wgmma_fence();
#pragma unroll
                for (int j = 0; j < 4; j++) wgmma_n128<1>(acc2, da + 64 * j, db + 128 * j, (k | j) != 0);
                wgmma_commit();
            }
            if (!wg) asm volatile("bar.arrive 3, 256;" ::: "memory");
            const uint32_t ob = sb + (wg ? 0 : OFF_U) + (warp & 3) * 8192, rr = 2 * (g & 3) + (g >> 2);
            const uint32_t xrow = 4 * (lane & 1) + ((lane >> 1) & 3);
            const uint32_t xb = sb + wg * 16384 + ((warp & 3) * 16 + (lane & 8) + xrow) * 128 + (((lane >> 4) ^ xrow) << 4);
            wgmma_wait<4>();
#pragma unroll
            for (int i = 0; i < 64; i++) asm volatile("" : "+f"(acc[i]) :: "memory");
            mbar_wait(bars + 8 * BAR_X, 1);
#pragma unroll
            for (int j = 0; j < 16; j += 2) {
                uint32_t xv[4];
                ldsm_x4(xv, (xb ^ ((j & 7) << 4)) + (j >> 3) * 8192);
#pragma unroll
                for (int i = 0; i < 4; i++) {
                    const uint32_t p = bf_mul2(xv[i], dk[j + (i >> 1)]);
                    const float sc = (i & 1) ? g1.y : g0.y;
                    acc[4 * j + 2 * i] = sc * fmaf(bf_lo(p), 0.5f, acc[4 * j + 2 * i]);
                    acc[4 * j + 2 * i + 1] = sc * fmaf(bf_hi(p), 0.5f, acc[4 * j + 2 * i + 1]);
                }
            }
            if (wg) asm volatile("bar.sync 4, 256;" ::: "memory");
            else asm volatile("bar.arrive 4, 256;" ::: "memory");
            wgmma_wait_all(acc2);
            if (tid == 0) PROF(17);
            if (tid == 128) PROF(18);
            const uint32_t oa = ob + rr * 128 + (((q >> 1) ^ rr) << 4) + (q & 1) * 8;
#pragma unroll
            for (int c = 0; c < 4; c++) {
#pragma unroll
                for (int j = 0; j < 4; j++) {
                    const int i = 16 * c + 4 * j;
                    sts64((oa ^ (j << 5)) + c * 2048, fmaf(g0.x, acc2[i], acc[i]), fmaf(g0.x, acc2[i + 1], acc[i + 1]));
                    sts64((oa ^ (j << 5)) + c * 2048 + 1024, fmaf(g1.x, acc2[i + 2], acc[i + 2]), fmaf(g1.x, acc2[i + 3], acc[i + 3]));
                }
                fence_proxy_async_smem();
                __syncwarp();
                if (elect()) tma_store_5d(&mapO, ob + c * 2048, (b2 >> 4) * 1024 + (b2 & 14) * 64 + 32 * c, 16 * (b & 1) + 2 * warp);
            }
            if (elect()) {
                bulk_commit();
                asm volatile("cp.async.bulk.wait_group.read 0;" ::: "memory");
            }
            if (tid == 0) PROF(19);
            if (tid == 224) PROF(20);
        }
        if (tid == 0) {
            const unsigned old = atomicAdd(&g_cnt[CNT_DONE * 32], 1u);
            if (old == 128) { g_cnt[CNT_DONE * 32] = 0; g_cnt[CNT_EPOCH * 32] = load_epoch(); }
        }
    } else {
        reg_dealloc<120>();
        const int t = tid - 256, w = warp - 8;
        if (w == 0 && main_cta && elect()) {
            mbar_expect_tx(bars + 8 * BAR_X, 32768);
            tma_load_4d(sb + OFF_U, &mapXs, bars + 8 * BAR_X, (b & 15) * 64, 0, 0, b >> 4);
            tma_load_4d(sb + OFF_U + 16384, &mapXs, bars + 8 * BAR_X, (b & 15) * 64 + 32, 0, 0, b >> 4);
        }
        const unsigned epoch = load_epoch();
        const bool real_cls = (cls & 127) == 0;
        const bool special = t < 4;
        const float R = 0.70710678118654752f;
        uint4 fa[4];
#pragma unroll
        for (int i = 0; i < 4; i++) fa[i] = __ldg((const uint4*)c_tab + i * 128 + t);
        float2 w1, w2, w3;
        {
            const int kk = (t >> 3) & 7, r = t & 7;
            float sn, cs;
            sincospif((float)(((cls + 256 * kk) * r) & 2047) * (1.f / 1024.f), &sn, &cs);
            sn *= 1.f / 1024.f; cs *= 1.f / 1024.f;
            const uint32_t gf = sb + OFF_G + kk * 16 + r * 2, gi = sb + OFF_G + 512 + r * 16 + kk * 2;
            if (t < 64) {
                sts16(gf, cs); sts16(gf + 128, real_cls ? 0.f : sn); sts16(gf + 256, -sn); sts16(gf + 384, real_cls ? 0.f : cs);
                sts16(gi, cs); sts16(gi + 128, -sn); sts16(gi + 256, sn); sts16(gi + 384, cs);
            }
            sincospif((float)(8 * w + g) * (1.f / 128.f), &sn, &cs);
            w1 = make_float2(cs, -sn); w2 = cmul(w1, w1); w3 = cmul(w1, w2);
        }
        if (main_cta) {
            const uint32_t ua = sb + OFF_U + (lane >> 4) * 8192 + (8 * w + (lane & 7)) * 64 + ((((lane >> 3) & 1) ^ ((lane >> 1) & 3)) << 4);
            mbar_wait(bars + 8 * BAR_X, 0);
            if (t == 0) PROF(8);
#pragma unroll 1
            for (int hf = 0; hf < 2; hf++) {
                float acc[64];
                const uint64_t db = make_desc(sb + OFF_U + hf * 16384, 4096, 512, 2);
                wgmma_fence();
                wgmma_rs_n128<0>(acc, fa[0], db); wgmma_rs_n128<1>(acc, fa[1], db + 64); wgmma_rs_n128<1>(acc, fa[2], db + 128); wgmma_rs_n128<1>(acc, fa[3], db + 192);
                wgmma_commit();
                wgmma_wait_all(acc);
                helper_sync();
#pragma unroll
                for (int jp = 0; jp < 2; jp++) {
                    float2 y[4][4];
#pragma unroll
                    for (int i = 0; i < 4; i++) {
                        const int o = 8 * jp + 4 * (i >> 1) + (i & 1);
#pragma unroll
                        for (int m = 0; m < 4; m++) y[i][m] = make_float2(acc[16 * m + o], acc[16 * m + o + 2]);
                    }
                    if (special) {
#pragma unroll
                        for (int i = 0; i < 4; i++) {
                            const float2 s0 = cadd(y[i][0], y[i][2]), s1 = csub(y[i][0], y[i][2]), s2 = cadd(y[i][1], y[i][3]), s3 = csub(y[i][1], y[i][3]);
                            const float b0 = y[i][0].y, b2 = y[i][2].y;
                            y[i][0] = make_float2(s0.x + s2.x, s0.x - s2.x);
                            y[i][1] = make_float2(s1.x, -s3.x);
                            y[i][2] = make_float2(fmaf(R, s3.y, b0), fmaf(-R, s2.y, -b2));
                            y[i][3] = make_float2(fmaf(-R, s3.y, b0), fmaf(-R, s2.y, b2));
                        }
                    } else {
#pragma unroll
                        for (int i = 0; i < 4; i++) {
                            y[i][1] = cmul(y[i][1], w1); y[i][2] = cmul(y[i][2], w2); y[i][3] = cmul(y[i][3], w3);
                            fft4(y[i][0], y[i][1], y[i][2], y[i][3]);
                        }
                    }
                    __syncwarp();
#pragma unroll
                    for (int c = 0; c < 4; c++)
                        stsm_x4((ua ^ (jp * 32)) + hf * 16384 + c * 2048, pack2(y[0][c].x, y[1][c].x), pack2(y[2][c].x, y[3][c].x),
                                pack2(y[0][c].y, y[1][c].y), pack2(y[2][c].y, y[3][c].y));
                }
                fence_proxy_async_smem();
                helper_sync();
                if (w == 0 && elect()) {
                    tma_store_4d(&mapU0, sb + OFF_U + hf * 16384, (b & 15) * 64 + hf * 32, 0, 0, b >> 4);
                    bulk_commit();
                }
            }
        }
        if (w == 0 && elect()) {
            PROF(21);
            if (main_cta) {
                bulk_wait0();
                signal_counter(&g_cnt[CNT_U * 32]);
            }
            PROF(9);
            mbar_expect_tx(bars + 8 * BAR_U, 32768);
            wait_counter(&g_cnt[CNT_U * 32], epoch * 128);
            PROF(11);
#pragma unroll 1
            for (int i = 0; i < 8; i++) {
                if ((i & 3) == 0) pace(prog);
                tma_load_4d(sb + OFF_U + i * 4096, &mapU2, bars + 8 * BAR_U, 0, 0, (i & 3) * 4, b == 128 ? 1 : b == 0 ? 0 : 2 * b + (i >> 2));
            }
        }
        fence_proxy_async_smem();
        helper_sync();
        mbar_wait(bars + 8 * BAR_U, 0);
#pragma unroll 1
        for (int hf = 0; hf < 2; hf++) radix8(sb, sb + OFF_G, hf, w, lane, 1);
        if (t == 0) PROF(22);
#pragma unroll 1
        for (int rr = 0; rr < 2; rr++) {
            const int k = cls + 256 * (2 * w + rr);
            const int od = k * 513, om = ((2048 - k) & 2047) * 513;
            uint32_t v[2][16][2], e[2][2];
#pragma unroll
            for (int pl = 0; pl < 2; pl++) {
                const bf16* wp = pl ? P.w_i : P.w_r;
#pragma unroll
                for (int i = 0; i < 8; i++) {
                    v[pl][i][0] = ldg16(wp + od + 2 * lane + 64 * i); v[pl][i][1] = ldg16(wp + od + 2 * lane + 64 * i + 1);
                    v[pl][8 + i][0] = ldg16(wp + om - 2 * lane + 512 - 64 * i); v[pl][8 + i][1] = ldg16(wp + om - 2 * lane + 511 - 64 * i);
                }
                e[pl][0] = ldg16(wp + om); e[pl][1] = ldg16(wp + od + 512);
            }
            if (main_cta) mbar_wait(bars + 8 * BAR_S0, 0);
            if (t == 0 && rr == 0) {
                mbar_expect_tx(bars + 8 * BAR_C, 12288);
                bulk_load(sb + OFF_F, c_tab + 2048, 12288, bars + 8 * BAR_C);
                bulk_prefetch_l2(c_inv + (b & 127) * 128, 1024);
                PROF(10);
            }
#pragma unroll
            for (int pl = 0; pl < 2; pl++) {
                if (lane == 0) {
                    v[pl][0][0] = pack2(fmaf(pl ? -0.5f : 0.5f, bf_lo(e[pl][0]), 0.5f * bf_lo(v[pl][0][0])), 0.f);
                    v[pl][8][0] = pack2(fmaf(pl ? -0.5f : 0.5f, bf_lo(e[pl][1]), 0.5f * bf_lo(v[pl][8][0])), 0.f);
                }
#pragma unroll
                for (int i = 0; i < 16; i++)
                    sts32(sb + OFF_W + (2 * w + rr) * 4096 + pl * 2048 + i * 128 + ((lane * 4) ^ ((i & 3) << 4)),
                          __byte_perm(v[pl][i][0], v[pl][i][1], 0x5410) ^ (pl && i >= 8 ? 0x80008000u : 0u));
            }
        }
        mbar_arrive(bars + 8 * BAR_C);
        if (t == 0) PROF(12);
        if (elect()) {
            if (w == 0) {
                unsigned t0;
                if (main_cta) {
#pragma unroll 1
                    for (int i = 0; i < 16; i++) {
                        if (i < 8) mbar_wait(bars + 8 * (BAR_H + (i >> 1)), 0);
                        else while (clock() - t0 < (i - 8) * PACE_H) { }
                        if (i == 0) bulk_store(g_gate + 16 * b, sb + OFF_GS, 128);
                        bulk_store(g_hT + (((i >> 3) * 16 + (b & 15)) * 64 + (i & 7) * 8 + (b >> 4)) * 4096, sb + OFF_HS + (i ^ 8) * 4096, 4096);
                        if ((i & 7) == 7) {
                            bulk_commit();
                            bulk_wait0();
                            signal_counter(&g_cnt[(CNT_H + (i >> 3)) * 32]);
                            t0 = clock();
                            PROF(i < 8 ? 26 : 2);
                        }
                    }
                    mbar_arrive(bars + 8 * BAR_HF);
                }
                mbar_wait(bars + 8 * BAR_R8, 0);
                t0 = clock();
#pragma unroll 1
                for (int i = 0; i < (real_cls ? 4 : 8); i++) {
                    while (clock() - t0 < i * PACE_V) { }
                    tma_store_4d(&mapU2, sb + OFF_U + i * 4096, 0, 0, (i & 3) * 4, b == 128 ? 1 : 2 * b + (i >> 2));
                }
                bulk_commit();
                bulk_wait0();
                signal_counter(&g_cnt[CNT_V * 32]);
                PROF(13);
            } else if (main_cta && w == 1) {
                mbar_wait(bars + 8 * BAR_G1, 0);
#pragma unroll 1
                for (int k = 0; k < 5; k++) load_c(k, k < 2 ? k + 3 : k - 2);
                wait_counter(&g_cnt[CNT_H * 32], epoch * 128);
                PROF(1);
#pragma unroll 1
                for (int k = 0; k < 5; k++) {
                    if (k == 2) mbar_wait(bars + 8 * BAR_CD, 0);
                    if (k == 3) mbar_wait(bars + 8 * BAR_HF, 0);
                    load_h(k, k < 2 ? k + 3 : k - 2);
                }
                int s = 3; uint32_t ph = 0;
#pragma unroll 1
                for (int k = 5; k < 36; k++) {
                    if ((k & 15) == 0) mbar_wait(bars + 8 * (BAR_H1 - 1 + (k >> 4)), 0);
                    mbar_wait(bars + 8 * (BAR_EMPTY2 + s), ph);
                    load_c(k, s);
                    load_h(k, s);
                    if (s == 2) ph ^= 1;
                    if (++s == 5) s = 0;
                }
            } else if (main_cta && w == 2) {
                mbar_wait(bars + 8 * BAR_CD, 0);
                mbar_expect_tx(bars + 8 * BAR_X, 32768);
                tma_load_3d(sb, &mapXe, bars + 8 * BAR_X, 0, 128 * (b & 1), b2 & ~1);
                tma_load_3d(sb + 16384, &mapXe, bars + 8 * BAR_X, 0, 128 * (b & 1) + 64, b2 & ~1);
                wait_counter(&g_cnt[(CNT_H + 1) * 32], epoch * 128);
                mbar_arrive(bars + 8 * BAR_H1);
                wait_counter(&g_cnt[CNT_V * 32], epoch * 129);
                mbar_arrive(bars + 8 * BAR_V);
                PROF(14);
            }
        }
    }
}

typedef CUresult (*PFN_encodeTiled)(CUtensorMap*, CUtensorMapDataType, cuuint32_t, void*, const cuuint64_t*, const cuuint64_t*,
                                    const cuuint32_t*, const cuuint32_t*, CUtensorMapInterleave, CUtensorMapSwizzle,
                                    CUtensorMapL2promotion, CUtensorMapFloatOOBfill);

static CUtensorMap make_map(PFN_encodeTiled enc, const void* ptr, int rank, const cuuint64_t* dims, const cuuint64_t* strides, const cuuint32_t* box,
                            CUtensorMapSwizzle sw = CU_TENSOR_MAP_SWIZZLE_128B, CUtensorMapDataType dt = CU_TENSOR_MAP_DATA_TYPE_BFLOAT16) {
    CUtensorMap m;
    cuuint32_t es[5] = {1, 1, 1, 1, 1};
    enc(&m, dt, rank, (void*)ptr, dims, strides, box, es, CU_TENSOR_MAP_INTERLEAVE_NONE,
        sw, CU_TENSOR_MAP_L2_PROMOTION_L2_128B, CU_TENSOR_MAP_FLOAT_OOB_FILL_NONE);
    return m;
}

extern "C" void kernel_launch(void* const* d_in, const int* in_sizes, int n_in, void* d_out, int out_size) {
    const bf16* x = (const bf16*)d_in[0];
    const bf16* wr = (const bf16*)d_in[1];
    const bf16* wi = (const bf16*)d_in[2];
    const bf16* Bre = (const bf16*)d_in[6];
    const bf16* Bim = (const bf16*)d_in[7];
    const bf16* Cre = (const bf16*)d_in[8];
    const bf16* Cim = (const bf16*)d_in[9];

    void* fn = nullptr;
    cudaDriverEntryPointQueryResult st;
    cudaGetDriverEntryPoint("cuTensorMapEncodeTiled", &fn, cudaEnableDefault, &st);
    PFN_encodeTiled enc = (PFN_encodeTiled)fn;
    void* p_U;
    cudaGetSymbolAddress(&p_U, g_U);

    Params P;
    P.lam_re = (const bf16*)d_in[4]; P.lam_im = (const bf16*)d_in[5]; P.log_dt = (const bf16*)d_in[10];
    P.dskip = (const bf16*)d_in[11]; P.gate_w = (const bf16*)d_in[12]; P.c_re = Cre; P.c_im = Cim; P.w_r = wr; P.w_i = wi;
    P.swapB = Bim < Bre;

    for (int c = 0; c < 68; c++) P.perm[c] = c < 4 ? 32 + 8 * c : c < 36 ? ((c - 4) & 24) + ((c - 5) & 7) : c < 64 ? 32 + (c - 36) / 7 * 8 + ((c - 37 + 7) % 7 + 1) : c;

    CUtensorMap mB, mX, mCre, mCim, mXs, mU0, mV, mU2, mXe, mO;
    {
        const bf16* lo = P.swapB ? Bim : Bre; const bf16* hi = P.swapB ? Bre : Bim;
        cuuint64_t d[4] = {1024, 8, 2, 128}, s[3] = {2048, (cuuint64_t)((const char*)hi - (const char*)lo), 16384};
        cuuint32_t bx[4] = {64, 8, 2, 8};
        mB = make_map(enc, lo, 4, d, s, bx);
    }
    {
        cuuint64_t d[4] = {1024, 2, 4, 928}, s[3] = {2048, 64 * 2048, 2 * 2048};
        cuuint32_t bx[4] = {64, 2, 4, 32};
        mX = make_map(enc, x, 4, d, s, bx);
    }
    {
        cuuint64_t d[3] = {64, 1024, 16}, s[2] = {2048, 128};
        cuuint32_t bx[3] = {64, 128, 1};
        mCre = make_map(enc, Cre, 3, d, s, bx);
        mCim = make_map(enc, Cim, 3, d, s, bx);
    }
    {
        cuuint64_t d[3] = {64, 256, 128}, s[2] = {16384, 128};
        cuuint32_t bx[3] = {64, 64, 2};
        mV = make_map(enc, p_U, 3, d, s, bx);
        mXe = make_map(enc, x, 3, d, s, bx);
    }
    {
        cuuint64_t d[5] = {8192, 2, 2, 2, 32}, s[4] = {16 * 4096, 32 * 4096, 8 * 4096, 64 * 4096};
        cuuint32_t bx[5] = {32, 2, 2, 2, 2};
        mO = make_map(enc, d_out, 5, d, s, bx, CU_TENSOR_MAP_SWIZZLE_128B, CU_TENSOR_MAP_DATA_TYPE_FLOAT32);
    }
    {
        cuuint64_t d[4] = {1024, 64, 4, 8}, s[3] = {32 * 2048, 8 * 2048, 2048};
        cuuint32_t bx[4] = {32, 64, 4, 1};
        mXs = make_map(enc, x, 4, d, s, bx, CU_TENSOR_MAP_SWIZZLE_64B);
    }
    {
        cuuint64_t d[4] = {1024, 128, 2, 8}, s[3] = {32768, 16384, 2048};
        cuuint32_t bx[4] = {32, 128, 2, 1};
        mU0 = make_map(enc, p_U, 4, d, s, bx, CU_TENSOR_MAP_SWIZZLE_64B);
    }
    {
        cuuint64_t d[4] = {64, 8, 16, 256}, s[3] = {2048, 128, 16384};
        cuuint32_t bx[4] = {64, 8, 4, 1};
        mU2 = make_map(enc, p_U, 4, d, s, bx);
    }
    cudaFuncSetAttribute(fused_kernel, cudaFuncAttributeMaxDynamicSharedMemorySize, SMEM_BYTES);
    fused_kernel<<<130, 384, SMEM_BYTES, cudaStreamPerThread>>>(mB, mX, mXs, mU0, mU2, mXe, mCre, mCim, mV, mO, P);
}
```

```cpp
#include <cuda_runtime.h>
#include <cuda_bf16.h>
#include <cuda.h>
#include <stdint.h>

typedef __nv_bfloat16 bf16;

__device__ const __align__(128) uint32_t c_tab[5120] = {
0x3f803f80,0xbf803f80,0x3f803f80,0xbf803f80,0x3f803f80,0xbf803f80,0x3f803f80,0xbf803f80,0x3f803f80,0xbf803f80,0x3f803f80,0xbf803f80,
0x3f803f80,0xbf803f80,0x3f803f80,0xbf803f80,0x3f7f3f80,0xbdc98000,0x3f223f35,0xbf46bf35,0x3f753f7b,0xbe95be48,0x3ef13f0e,0xbf62bf55,
0x3f623f6d,0xbef1bec4,0x3e953ec4,0xbf75bf6d,0x3f463f55,0xbf22bf0e,0x3dc93e48,0xbf7fbf7b,0x3f7b3f80,0xbe488000,0xbe480000,0xbf7bbf80,
0x3f553f6d,0xbf0ebec4,0xbf0ebec4,0xbf55bf6d,0x3f0e3f35,0xbf55bf35,0xbf55bf35,0xbf0ebf35,0x3e483ec4,0xbf7bbf6d,0xbf7bbf6d,0xbe48bec4,
0x3f753f80,0xbe958000,0xbf62bf35,0xbef1bf35,0x3f223f55,0xbf46bf0e,0xbf7fbf7b,0x3dc9be48,0x3dc93ec4,0xbf7fbf6d,0xbf46bf6d,0x3f223ec4,
0xbef1be48,0xbf62bf7b,0xbe95bf0e,0x3f753f55,0x3f6d3f80,0xbec48000,0xbf6dbf80,0x3ec48000,0x3ec43f35,0xbf6dbf35,0xbec4bf35,0x3f6d3f35,
0xbec40000,0xbf6dbf80,0x3ec40000,0x3f6d3f80,0xbf6dbf35,0xbec4bf35,0x3f6d3f35,0x3ec43f35,0x3f623f80,0xbef18000,0xbe95bf35,0x3f753f35,
0x3dc93f0e,0xbf7fbf55,0x3f223e48,0x3f463f7b,0xbf46bec4,0xbf22bf6d,0x3f7f3f6d,0xbdc93ec4,0xbf75bf7b,0x3e95be48,0x3ef13f55,0xbf62bf0e,
0x3f553f80,0xbf0e8000,0x3f0e0000,0x3f553f80,0xbe483ec4,0xbf7bbf6d,0x3f7b3f6d,0xbe483ec4,0xbf7bbf35,0xbe48bf35,0x3e483f35,0xbf7bbf35,
0xbf0ebf6d,0x3f553ec4,0xbf55bec4,0xbf0ebf6d,0x3f463f80,0xbf228000,0x3f7f3f35,0x3dc93f35,0xbef13e48,0xbf62bf7b,0x3e953f55,0xbf75bf0e,
0xbf75bf6d,0x3e95bec4,0xbf62bec4,0xbef1bf6d,0x3dc9bf0e,0x3f7f3f55,0xbf22bf7b,0x3f463e48,0x3f353f80,0xbf358000,0x3f353f80,0xbf358000,
0xbf350000,0xbf35bf80,0xbf350000,0xbf35bf80,0xbf35bf80,0x3f358000,0xbf35bf80,0x3f358000,0x3f350000,0x3f353f80,0x3f350000,0x3f353f80,
0x3f223f80,0xbf468000,0xbdc93f35,0xbf7fbf35,0xbf62be48,0xbef1bf7b,0xbf75bf55,0x3e95bf0e,0xbe95bf6d,0x3f753ec4,0x3ef1bec4,0x3f623f6d,
0x3f7f3f0e,0x3dc93f55,0x3f463f7b,0xbf223e48,0x3f0e3f80,0xbf558000,0xbf550000,0xbf0ebf80,0xbf7bbec4,0xbe48bf6d,0xbe48bf6d,0x3f7b3ec4,
0x3e48bf35,0x3f7b3f35,0x3f7b3f35,0xbe483f35,0x3f553f6d,0xbf0e3ec4,0xbf0e3ec4,0xbf55bf6d,0x3ef13f80,0xbf628000,0xbf75bf35,0x3e95bf35,
0xbf7fbf0e,0x3dc9bf55,0x3f46be48,0x3f223f7b,0x3f22bec4,0x3f463f6d,0x3dc93f6d,0xbf7fbec4,0x3e953f7b,0xbf75be48,0xbf62bf55,0x3ef1bf0e,
0x3ec43f80,0xbf6d8000,0xbec4bf80,0x3f6d8000,0xbf6dbf35,0x3ec4bf35,0x3f6d3f35,0xbec43f35,0x3f6d0000,0x3ec43f80,0xbf6d0000,0xbec4bf80,
0xbec43f35,0xbf6dbf35,0x3ec4bf35,0x3f6d3f35,0x3e953f80,0xbf758000,0x3ef1bf35,0x3f623f35,0xbf46bf55,0x3f22bf0e,0x3dc93f7b,0xbf7fbe48,
0x3f7f3ec4,0xbdc93f6d,0xbf22bf6d,0x3f46bec4,0xbf623e48,0xbef1bf7b,0x3f753f0e,0xbe953f55,0x3e483f80,0xbf7b8000,0x3f7b0000,0x3e483f80,
0xbf0ebf6d,0x3f55bec4,0xbf553ec4,0xbf0ebf6d,0x3f553f35,0xbf0e3f35,0x3f0ebf35,0x3f553f35,0xbf7bbec4,0x3e48bf6d,0xbe483f6d,0xbf7bbec4,
0x3dc93f80,0xbf7f8000,0x3f463f35,0xbf223f35,0xbe95bf7b,0x3f75be48,0xbf62bf0e,0x3ef1bf55,0x3ef13f6d,0xbf623ec4,0x3f753ec4,0xbe953f6d,
0xbf22bf55,0x3f46bf0e,0xbf7fbe48,0x3dc9bf7b,0x3f80,0xbf808000,0x3f80,0xbf808000,0xbf80,0x3f808000,0xbf80,0x3f808000,
0x3f80,0xbf808000,0x3f80,0xbf808000,0xbf80,0x3f808000,0xbf80,0x3f808000,0xbdc93f80,0xbf7f8000,0xbf463f35,0xbf22bf35,
0x3e95bf7b,0x3f753e48,0x3f62bf0e,0x3ef13f55,0xbef13f6d,0xbf62bec4,0xbf753ec4,0xbe95bf6d,0x3f22bf55,0x3f463f0e,0x3f7fbe48,0x3dc93f7b,
0xbe483f80,0xbf7b8000,0xbf7b0000,0x3e48bf80,0x3f0ebf6d,0x3f553ec4,0x3f553ec4,0xbf0e3f6d,0xbf553f35,0xbf0ebf35,0xbf0ebf35,0x3f55bf35,
0x3f7bbec4,0x3e483f6d,0x3e483f6d,0xbf7b3ec4,0xbe953f80,0xbf758000,0xbef1bf35,0x3f62bf35,0x3f46bf55,0x3f223f0e,0xbdc93f7b,0xbf7f3e48,
0xbf7f3ec4,0xbdc9bf6d,0x3f22bf6d,0x3f463ec4,0x3f623e48,0xbef13f7b,0xbf753f0e,0xbe95bf55,0xbec43f80,0xbf6d8000,0x3ec4bf80,0x3f6d8000,
0x3f6dbf35,0x3ec43f35,0xbf6d3f35,0xbec4bf35,0xbf6d0000,0x3ec4bf80,0x3f6d0000,0xbec43f80,0x3ec43f35,0xbf6d3f35,0xbec4bf35,0x3f6dbf35,
0xbef13f80,0xbf628000,0x3f75bf35,0x3e953f35,0x3f7fbf0e,0x3dc93f55,0xbf46be48,0x3f22bf7b,0xbf22bec4,0x3f46bf6d,0xbdc93f6d,0xbf7f3ec4,
0xbe953f7b,0xbf753e48,0x3f62bf55,0x3ef13f0e,0xbf0e3f80,0xbf558000,0x3f550000,0xbf0e3f80,0x3f7bbec4,0xbe483f6d,0x3e48bf6d,0x3f7bbec4,
0xbe48bf35,0x3f7bbf35,0xbf7b3f35,0xbe48bf35,0xbf553f6d,0xbf0ebec4,0x3f0e3ec4,0xbf553f6d,0xbf223f80,0xbf468000,0x3dc93f35,0xbf7f3f35,
0x3f62be48,0xbef13f7b,0x3f75bf55,0x3e953f0e,0x3e95bf6d,0x3f75bec4,0xbef1bec4,0x3f62bf6d,0xbf7f3f0e,0x3dc9bf55,0xbf463f7b,0xbf22be48,
0xbf353f80,0xbf358000,0xbf353f80,0xbf358000,0x3f350000,0xbf353f80,0x3f350000,0xbf353f80,0x3f35bf80,0x3f358000,0x3f35bf80,0x3f358000,
0xbf350000,0x3f35bf80,0xbf350000,0x3f35bf80,0xbf463f80,0xbf228000,0xbf7f3f35,0x3dc9bf35,0x3ef13e48,0xbf623f7b,0xbe953f55,0xbf753f0e,
0x3f75bf6d,0x3e953ec4,0x3f62bec4,0xbef13f6d,0xbdc9bf0e,0x3f7fbf55,0x3f22bf7b,0x3f46be48,0xbf553f80,0xbf0e8000,0xbf0e0000,0x3f55bf80,
0x3e483ec4,0xbf7b3f6d,0xbf7b3f6d,0xbe48bec4,0x3f7bbf35,0xbe483f35,0xbe483f35,0xbf7b3f35,0x3f0ebf6d,0x3f55bec4,0x3f55bec4,0xbf0e3f6d,
0xbf623f80,0xbef18000,0x3e95bf35,0x3f75bf35,0xbdc93f0e,0xbf7f3f55,0xbf223e48,0x3f46bf7b,0x3f46bec4,0xbf223f6d,0xbf7f3f6d,0xbdc9bec4,
0x3f75bf7b,0x3e953e48,0xbef13f55,0xbf623f0e,0xbf6d3f80,0xbec48000,0x3f6dbf80,0x3ec48000,0xbec43f35,0xbf6d3f35,0x3ec4bf35,0x3f6dbf35,
0x3ec40000,0xbf6d3f80,0xbec40000,0x3f6dbf80,0x3f6dbf35,0xbec43f35,0xbf6d3f35,0x3ec4bf35,0xbf753f80,0xbe958000,0x3f62bf35,0xbef13f35,
0xbf223f55,0xbf463f0e,0x3f7fbf7b,0x3dc93e48,0xbdc93ec4,0xbf7f3f6d,0x3f46bf6d,0x3f22bec4,0x3ef1be48,0xbf623f7b,0x3e95bf0e,0x3f75bf55,
0xbf7b3f80,0xbe488000,0x3e480000,0xbf7b3f80,0xbf553f6d,0xbf0e3ec4,0x3f0ebec4,0xbf553f6d,0xbf0e3f35,0xbf553f35,0x3f55bf35,0xbf0e3f35,
0xbe483ec4,0xbf7b3f6d,0x3f7bbf6d,0xbe483ec4,0xbf7f3f80,0xbdc98000,0xbf223f35,0xbf463f35,0xbf753f7b,0xbe953e48,0xbef13f0e,0xbf623f55,
0xbf623f6d,0xbef13ec4,0xbe953ec4,0xbf753f6d,0xbf463f55,0xbf223f0e,0xbdc93e48,0xbf7f3f7b,0x3f803f80,0xbf803f80,0x3f803f80,0xbf803f80,
0x3f803f80,0xbf803f80,0x3f803f80,0xbf803f80,0x3f803f80,0xbf803f80,0x3f803f80,0xbf803f80,0x3f803f80,0xbf803f80,0x3f803f80,0xbf803f80,
0xbdc90000,0xbf7fbf80,0xbf46bf35,0xbf22bf35,0xbe95be48,0xbf75bf7b,0xbf62bf55,0xbef1bf0e,0xbef1bec4,0xbf62bf6d,0xbf75bf6d,0xbe95bec4,
0xbf22bf0e,0xbf46bf55,0xbf7fbf7b,0xbdc9be48,0xbf7bbf80,0x3e488000,0x3e480000,0x3f7b3f80,0xbf55bf6d,0x3f0e3ec4,0x3f0e3ec4,0x3f553f6d,
0xbf0ebf35,0x3f553f35,0x3f553f35,0x3f0e3f35,0xbe48bec4,0x3f7b3f6d,0x3f7b3f6d,0x3e483ec4,0x3e950000,0x3f753f80,0x3ef13f35,0xbf62bf35,
0x3f463f0e,0x3f223f55,0xbdc93e48,0xbf7fbf7b,0x3f7f3f6d,0x3dc93ec4,0xbf22bec4,0xbf46bf6d,0x3f623f7b,0xbef1be48,0xbf75bf55,0xbe95bf0e,
0x3f6d3f80,0xbec48000,0xbf6dbf80,0x3ec48000,0x3ec43f35,0xbf6dbf35,0xbec4bf35,0x3f6d3f35,0xbec40000,0xbf6dbf80,0x3ec40000,0x3f6d3f80,
0xbf6dbf35,0xbec4bf35,0x3f6d3f35,0x3ec43f35,0xbef10000,0xbf62bf80,0x3f753f35,0x3e953f35,0xbf7fbf55,0xbdc9bf0e,0x3f463f7b,0xbf22be48,
0xbf22bf6d,0x3f463ec4,0xbdc93ec4,0xbf7fbf6d,0x3e95be48,0x3f753f7b,0xbf62bf0e,0xbef1bf55,0xbf55bf80,0x3f0e8000,0xbf0e0000,0xbf55bf80,
0x3e48bec4,0x3f7b3f6d,0xbf7bbf6d,0x3e48bec4,0x3f7b3f35,0x3e483f35,0xbe48bf35,0x3f7b3f35,0x3f0e3f6d,0xbf55bec4,0x3f553ec4,0x3f0e3f6d,
0x3f220000,0x3f463f80,0xbdc9bf35,0x3f7f3f35,0x3f623f7b,0xbef13e48,0x3f753f0e,0x3e953f55,0xbe953ec4,0xbf75bf6d,0x3ef13f6d,0xbf62bec4,
0xbf7fbf55,0x3dc9bf0e,0xbf46be48,0xbf22bf7b,0x3f353f80,0xbf358000,0x3f353f80,0xbf358000,0xbf350000,0xbf35bf80,0xbf350000,0xbf35bf80,
0xbf35bf80,0x3f358000,0xbf35bf80,0x3f358000,0x3f350000,0x3f353f80,0x3f350000,0x3f353f80,0xbf460000,0xbf22bf80,0xbf7fbf35,0x3dc9bf35,
0xbef1bf7b,0x3f623e48,0x3e95bf0e,0x3f753f55,0x3f753ec4,0x3e953f6d,0x3f623f6d,0xbef13ec4,0x3dc93f55,0xbf7fbf0e,0xbf223e48,0xbf46bf7b,
0xbf0ebf80,0x3f558000,0x3f550000,0x3f0e3f80,0x3f7b3ec4,0x3e483f6d,0x3e483f6d,0xbf7bbec4,0xbe483f35,0xbf7bbf35,0xbf7bbf35,0x3e48bf35,
0xbf55bf6d,0x3f0ebec4,0x3f0ebec4,0x3f553f6d,0x3f620000,0x3ef13f80,0xbe953f35,0xbf75bf35,0xbdc93f55,0xbf7fbf0e,0xbf22bf7b,0x3f46be48,
0xbf46bf6d,0x3f22bec4,0x3f7f3ec4,0x3dc93f6d,0x3f753e48,0x3e953f7b,0xbef13f0e,0xbf62bf55,0x3ec43f80,0xbf6d8000,0xbec4bf80,0x3f6d8000,
0xbf6dbf35,0x3ec4bf35,0x3f6d3f35,0xbec43f35,0x3f6d0000,0x3ec43f80,0xbf6d0000,0xbec4bf80,0xbec43f35,0xbf6dbf35,0x3ec4bf35,0x3f6d3f35,
0xbf750000,0xbe95bf80,0x3f623f35,0xbef13f35,0x3f22bf0e,0x3f463f55,0xbf7fbe48,0xbdc9bf7b,0xbdc93f6d,0xbf7fbec4,0x3f46bec4,0x3f223f6d,
0xbef1bf7b,0x3f62be48,0xbe953f55,0xbf75bf0e,0xbe48bf80,0x3f7b8000,0xbf7b0000,0xbe48bf80,0x3f0e3f6d,0xbf553ec4,0x3f55bec4,0x3f0e3f6d,
0xbf55bf35,0x3f0ebf35,0xbf0e3f35,0xbf55bf35,0x3f7b3ec4,0xbe483f6d,0x3e48bf6d,0x3f7b3ec4,0x3f7f0000,0x3dc93f80,0x3f22bf35,0x3f463f35,
0xbf753e48,0xbe95bf7b,0xbef13f55,0xbf62bf0e,0x3f62bec4,0x3ef13f6d,0x3e95bf6d,0x3f753ec4,0xbf463f0e,0xbf22bf55,0xbdc93f7b,0xbf7fbe48,
0x3f80,0xbf808000,0x3f80,0xbf808000,0xbf80,0x3f808000,0xbf80,0x3f808000,0x3f80,0xbf808000,0x3f80,0xbf808000,
0xbf80,0x3f808000,0xbf80,0x3f808000,0xbf7f0000,0x3dc9bf80,0xbf22bf35,0x3f46bf35,0x3f753e48,0xbe953f7b,0x3ef13f55,0xbf623f0e,
0xbf62bec4,0x3ef1bf6d,0xbe95bf6d,0x3f75bec4,0x3f463f0e,0xbf223f55,0x3dc93f7b,0xbf7f3e48,0x3e48bf80,0x3f7b8000,0x3f7b0000,0xbe483f80,
0xbf0e3f6d,0xbf55bec4,0xbf55bec4,0x3f0ebf6d,0x3f55bf35,0x3f0e3f35,0x3f0e3f35,0xbf553f35,0xbf7b3ec4,0xbe48bf6d,0xbe48bf6d,0x3f7bbec4,
0x3f750000,0xbe953f80,0xbf623f35,0xbef1bf35,0xbf22bf0e,0x3f46bf55,0x3f7fbe48,0xbdc93f7b,0x3dc93f6d,0xbf7f3ec4,0xbf46bec4,0x3f22bf6d,
0x3ef1bf7b,0x3f623e48,0x3e953f55,0xbf753f0e,0xbec43f80,0xbf6d8000,0x3ec4bf80,0x3f6d8000,0x3f6dbf35,0x3ec43f35,0xbf6d3f35,0xbec4bf35,
0xbf6d0000,0x3ec4bf80,0x3f6d0000,0xbec43f80,0x3ec43f35,0xbf6d3f35,0xbec4bf35,0x3f6dbf35,0xbf620000,0x3ef1bf80,0x3e953f35,0xbf753f35,
0x3dc93f55,0xbf7f3f0e,0x3f22bf7b,0x3f463e48,0x3f46bf6d,0x3f223ec4,0xbf7f3ec4,0x3dc9bf6d,0xbf753e48,0x3e95bf7b,0x3ef13f0e,0xbf623f55,
0x3f0ebf80,0x3f558000,0xbf550000,0x3f0ebf80,0xbf7b3ec4,0x3e48bf6d,0xbe483f6d,0xbf7b3ec4,0x3e483f35,0xbf7b3f35,0x3f7bbf35,0x3e483f35,
0x3f55bf6d,0x3f0e3ec4,0xbf0ebec4,0x3f55bf6d,0x3f460000,0xbf223f80,0x3f7fbf35,0x3dc93f35,0x3ef1bf7b,0x3f62be48,0xbe95bf0e,0x3f75bf55,
0xbf753ec4,0x3e95bf6d,0xbf623f6d,0xbef1bec4,0xbdc93f55,0xbf7f3f0e,0x3f223e48,0xbf463f7b,0xbf353f80,0xbf358000,0xbf353f80,0xbf358000,
0x3f350000,0xbf353f80,0x3f350000,0xbf353f80,0x3f35bf80,0x3f358000,0x3f35bf80,0x3f358000,0xbf350000,0x3f35bf80,0xbf350000,0x3f35bf80,
0xbf220000,0x3f46bf80,0x3dc9bf35,0x3f7fbf35,0xbf623f7b,0xbef1be48,0xbf753f0e,0x3e95bf55,0x3e953ec4,0xbf753f6d,0xbef13f6d,0xbf623ec4,
0x3f7fbf55,0x3dc93f0e,0x3f46be48,0xbf223f7b,0x3f55bf80,0x3f0e8000,0x3f0e0000,0xbf553f80,0xbe48bec4,0x3f7bbf6d,0x3f7bbf6d,0x3e483ec4,
0xbf7b3f35,0x3e48bf35,0x3e48bf35,0x3f7bbf35,0xbf0e3f6d,0xbf553ec4,0xbf553ec4,0x3f0ebf6d,0x3ef10000,0xbf623f80,0xbf753f35,0x3e95bf35,
0x3f7fbf55,0xbdc93f0e,0xbf463f7b,0xbf223e48,0x3f22bf6d,0x3f46bec4,0x3dc93ec4,0xbf7f3f6d,0xbe95be48,0x3f75bf7b,0x3f62bf0e,0xbef13f55,
0xbf6d3f80,0xbec48000,0x3f6dbf80,0x3ec48000,0xbec43f35,0xbf6d3f35,0x3ec4bf35,0x3f6dbf35,0x3ec40000,0xbf6d3f80,0xbec40000,0x3f6dbf80,
0x3f6dbf35,0xbec43f35,0xbf6d3f35,0x3ec4bf35,0xbe950000,0x3f75bf80,0xbef13f35,0xbf623f35,0xbf463f0e,0x3f22bf55,0x3dc93e48,0xbf7f3f7b,
0xbf7f3f6d,0x3dc9bec4,0x3f22bec4,0xbf463f6d,0xbf623f7b,0xbef13e48,0x3f75bf55,0xbe953f0e,0x3f7bbf80,0x3e488000,0xbe480000,0x3f7bbf80,
0x3f55bf6d,0x3f0ebec4,0xbf0e3ec4,0x3f55bf6d,0x3f0ebf35,0x3f55bf35,0xbf553f35,0x3f0ebf35,0x3e48bec4,0x3f7bbf6d,0xbf7b3f6d,0x3e48bec4,
0x3dc90000,0xbf7f3f80,0x3f46bf35,0xbf223f35,0x3e95be48,0xbf753f7b,0x3f62bf55,0xbef13f0e,0x3ef1bec4,0xbf623f6d,0x3f75bf6d,0xbe953ec4,
0x3f22bf0e,0xbf463f55,0x3f7fbf7b,0xbdc93e48,0x3f803f80,0xbf803f80,0x3f803f80,0xbf803f80,0x3f803f80,0xbf803f80,0x3f803f80,0xbf803f80,
0x3f803f80,0xbf803f80,0x3f803f80,0xbf803f80,0x3f803f80,0xbf803f80,0x3f803f80,0xbf803f80,0xbf7fbf80,0x3dc98000,0xbf22bf35,0x3f463f35,
0xbf75bf7b,0x3e953e48,0xbef1bf0e,0x3f623f55,0xbf62bf6d,0x3ef13ec4,0xbe95bec4,0x3f753f6d,0xbf46bf55,0x3f223f0e,0xbdc9be48,0x3f7f3f7b,
0x3f7b3f80,0xbe488000,0xbe480000,0xbf7bbf80,0x3f553f6d,0xbf0ebec4,0xbf0ebec4,0xbf55bf6d,0x3f0e3f35,0xbf55bf35,0xbf55bf35,0xbf0ebf35,
0x3e483ec4,0xbf7bbf6d,0xbf7bbf6d,0xbe48bec4,0xbf75bf80,0x3e958000,0x3f623f35,0x3ef13f35,0xbf22bf55,0x3f463f0e,0x3f7f3f7b,0xbdc93e48,
0xbdc9bec4,0x3f7f3f6d,0x3f463f6d,0xbf22bec4,0x3ef13e48,0x3f623f7b,0x3e953f0e,0xbf75bf55,0x3f6d3f80,0xbec48000,0xbf6dbf80,0x3ec48000,
0x3ec43f35,0xbf6dbf35,0xbec4bf35,0x3f6d3f35,0xbec40000,0xbf6dbf80,0x3ec40000,0x3f6d3f80,0xbf6dbf35,0xbec4bf35,0x3f6d3f35,0x3ec43f35,
0xbf62bf80,0x3ef18000,0x3e953f35,0xbf75bf35,0xbdc9bf0e,0x3f7f3f55,0xbf22be48,0xbf46bf7b,0x3f463ec4,0x3f223f6d,0xbf7fbf6d,0x3dc9bec4,
0x3f753f7b,0xbe953e48,0xbef1bf55,0x3f623f0e,0x3f553f80,0xbf0e8000,0x3f0e0000,0x3f553f80,0xbe483ec4,0xbf7bbf6d,0x3f7b3f6d,0xbe483ec4,
0xbf7bbf35,0xbe48bf35,0x3e483f35,0xbf7bbf35,0xbf0ebf6d,0x3f553ec4,0xbf55bec4,0xbf0ebf6d,0xbf46bf80,0x3f228000,0xbf7fbf35,0xbdc9bf35,
0x3ef1be48,0x3f623f7b,0xbe95bf55,0x3f753f0e,0x3f753f6d,0xbe953ec4,0x3f623ec4,0x3ef13f6d,0xbdc93f0e,0xbf7fbf55,0x3f223f7b,0xbf46be48,
0x3f353f80,0xbf358000,0x3f353f80,0xbf358000,0xbf350000,0xbf35bf80,0xbf350000,0xbf35bf80,0xbf35bf80,0x3f358000,0xbf35bf80,0x3f358000,
0x3f350000,0x3f353f80,0x3f350000,0x3f353f80,0xbf22bf80,0x3f468000,0x3dc9bf35,0x3f7f3f35,0x3f623e48,0x3ef13f7b,0x3f753f55,0xbe953f0e,
0x3e953f6d,0xbf75bec4,0xbef13ec4,0xbf62bf6d,0xbf7fbf0e,0xbdc9bf55,0xbf46bf7b,0x3f22be48,0x3f0e3f80,0xbf558000,0xbf550000,0xbf0ebf80,
0xbf7bbec4,0xbe48bf6d,0xbe48bf6d,0x3f7b3ec4,0x3e48bf35,0x3f7b3f35,0x3f7b3f35,0xbe483f35,0x3f553f6d,0xbf0e3ec4,0xbf0e3ec4,0xbf55bf6d,
0xbef1bf80,0x3f628000,0x3f753f35,0xbe953f35,0x3f7f3f0e,0xbdc93f55,0xbf463e48,0xbf22bf7b,0xbf223ec4,0xbf46bf6d,0xbdc9bf6d,0x3f7f3ec4,
0xbe95bf7b,0x3f753e48,0x3f623f55,0xbef13f0e,0x3ec43f80,0xbf6d8000,0xbec4bf80,0x3f6d8000,0xbf6dbf35,0x3ec4bf35,0x3f6d3f35,0xbec43f35,
0x3f6d0000,0x3ec43f80,0xbf6d0000,0xbec4bf80,0xbec43f35,0xbf6dbf35,0x3ec4bf35,0x3f6d3f35,0xbe95bf80,0x3f758000,0xbef13f35,0xbf62bf35,
0x3f463f55,0xbf223f0e,0xbdc9bf7b,0x3f7f3e48,0xbf7fbec4,0x3dc9bf6d,0x3f223f6d,0xbf463ec4,0x3f62be48,0x3ef13f7b,0xbf75bf0e,0x3e95bf55,
0x3e483f80,0xbf7b8000,0x3f7b0000,0x3e483f80,0xbf0ebf6d,0x3f55bec4,0xbf553ec4,0xbf0ebf6d,0x3f553f35,0xbf0e3f35,0x3f0ebf35,0x3f553f35,
0xbf7bbec4,0x3e48bf6d,0xbe483f6d,0xbf7bbec4,0xbdc9bf80,0x3f7f8000,0xbf46bf35,0x3f22bf35,0x3e953f7b,0xbf753e48,0x3f623f0e,0xbef13f55,
0xbef1bf6d,0x3f62bec4,0xbf75bec4,0x3e95bf6d,0x3f223f55,0xbf463f0e,0x3f7f3e48,0xbdc93f7b,0x3f80,0xbf808000,0x3f80,0xbf808000,
0xbf80,0x3f808000,0xbf80,0x3f808000,0x3f80,0xbf808000,0x3f80,0xbf808000,0xbf80,0x3f808000,0xbf80,0x3f808000,
0x3dc9bf80,0x3f7f8000,0x3f46bf35,0x3f223f35,0xbe953f7b,0xbf75be48,0xbf623f0e,0xbef1bf55,0x3ef1bf6d,0x3f623ec4,0x3f75bec4,0x3e953f6d,
0xbf223f55,0xbf46bf0e,0xbf7f3e48,0xbdc9bf7b,0xbe483f80,0xbf7b8000,0xbf7b0000,0x3e48bf80,0x3f0ebf6d,0x3f553ec4,0x3f553ec4,0xbf0e3f6d,
0xbf553f35,0xbf0ebf35,0xbf0ebf35,0x3f55bf35,0x3f7bbec4,0x3e483f6d,0x3e483f6d,0xbf7b3ec4,0x3e95bf80,0x3f758000,0x3ef13f35,0xbf623f35,
0xbf463f55,0xbf22bf0e,0x3dc9bf7b,0x3f7fbe48,0x3f7fbec4,0x3dc93f6d,0xbf223f6d,0xbf46bec4,0xbf62be48,0x3ef1bf7b,0x3f75bf0e,0x3e953f55,
0xbec43f80,0xbf6d8000,0x3ec4bf80,0x3f6d8000,0x3f6dbf35,0x3ec43f35,0xbf6d3f35,0xbec4bf35,0xbf6d0000,0x3ec4bf80,0x3f6d0000,0xbec43f80,
0x3ec43f35,0xbf6d3f35,0xbec4bf35,0x3f6dbf35,0x3ef1bf80,0x3f628000,0xbf753f35,0xbe95bf35,0xbf7f3f0e,0xbdc9bf55,0x3f463e48,0xbf223f7b,
0x3f223ec4,0xbf463f6d,0x3dc9bf6d,0x3f7fbec4,0x3e95bf7b,0x3f75be48,0xbf623f55,0xbef1bf0e,0xbf0e3f80,0xbf558000,0x3f550000,0xbf0e3f80,
0x3f7bbec4,0xbe483f6d,0x3e48bf6d,0x3f7bbec4,0xbe48bf35,0x3f7bbf35,0xbf7b3f35,0xbe48bf35,0xbf553f6d,0xbf0ebec4,0x3f0e3ec4,0xbf553f6d,
0x3f22bf80,0x3f468000,0xbdc9bf35,0x3f7fbf35,0xbf623e48,0x3ef1bf7b,0xbf753f55,0xbe95bf0e,0xbe953f6d,0xbf753ec4,0x3ef13ec4,0xbf623f6d,
0x3f7fbf0e,0xbdc93f55,0x3f46bf7b,0x3f223e48,0xbf353f80,0xbf358000,0xbf353f80,0xbf358000,0x3f350000,0xbf353f80,0x3f350000,0xbf353f80,
0x3f35bf80,0x3f358000,0x3f35bf80,0x3f358000,0xbf350000,0x3f35bf80,0xbf350000,0x3f35bf80,0x3f46bf80,0x3f228000,0x3f7fbf35,0xbdc93f35,
0xbef1be48,0x3f62bf7b,0x3e95bf55,0x3f75bf0e,0xbf753f6d,0xbe95bec4,0xbf623ec4,0x3ef1bf6d,0x3dc93f0e,0xbf7f3f55,0xbf223f7b,0xbf463e48,
0xbf553f80,0xbf0e8000,0xbf0e0000,0x3f55bf80,0x3e483ec4,0xbf7b3f6d,0xbf7b3f6d,0xbe48bec4,0x3f7bbf35,0xbe483f35,0xbe483f35,0xbf7b3f35,
0x3f0ebf6d,0x3f55bec4,0x3f55bec4,0xbf0e3f6d,0x3f62bf80,0x3ef18000,0xbe953f35,0xbf753f35,0x3dc9bf0e,0x3f7fbf55,0x3f22be48,0xbf463f7b,
0xbf463ec4,0x3f22bf6d,0x3f7fbf6d,0x3dc93ec4,0xbf753f7b,0xbe95be48,0x3ef1bf55,0x3f62bf0e,0xbf6d3f80,0xbec48000,0x3f6dbf80,0x3ec48000,
0xbec43f35,0xbf6d3f35,0x3ec4bf35,0x3f6dbf35,0x3ec40000,0xbf6d3f80,0xbec40000,0x3f6dbf80,0x3f6dbf35,0xbec43f35,0xbf6d3f35,0x3ec4bf35,
0x3f75bf80,0x3e958000,0xbf623f35,0x3ef1bf35,0x3f22bf55,0x3f46bf0e,0xbf7f3f7b,0xbdc9be48,0x3dc9bec4,0x3f7fbf6d,0xbf463f6d,0xbf223ec4,
0xbef13e48,0x3f62bf7b,0xbe953f0e,0xbf753f55,0xbf7b3f80,0xbe488000,0x3e480000,0xbf7b3f80,0xbf553f6d,0xbf0e3ec4,0x3f0ebec4,0xbf553f6d,
0xbf0e3f35,0xbf553f35,0x3f55bf35,0xbf0e3f35,0xbe483ec4,0xbf7b3f6d,0x3f7bbf6d,0xbe483ec4,0x3f7fbf80,0x3dc98000,0x3f22bf35,0x3f46bf35,
0x3f75bf7b,0x3e95be48,0x3ef1bf0e,0x3f62bf55,0x3f62bf6d,0x3ef1bec4,0x3e95bec4,0x3f75bf6d,0x3f46bf55,0x3f22bf0e,0x3dc9be48,0x3f7fbf7b,
0x3f803f80,0xbf803f80,0x3f803f80,0xbf803f80,0x3f803f80,0xbf803f80,0x3f803f80,0xbf803f80,0x3f803f80,0xbf803f80,0x3f803f80,0xbf803f80,
0x3f803f80,0xbf803f80,0x3f803f80,0xbf803f80,0x3dc90000,0x3f7f3f80,0x3f463f35,0x3f223f35,0x3e953e48,0x3f753f7b,0x3f623f55,0x3ef13f0e,
0x3ef13ec4,0x3f623f6d,0x3f753f6d,0x3e953ec4,0x3f223f0e,0x3f463f55,0x3f7f3f7b,0x3dc93e48,0xbf7bbf80,0x3e488000,0x3e480000,0x3f7b3f80,
0xbf55bf6d,0x3f0e3ec4,0x3f0e3ec4,0x3f553f6d,0xbf0ebf35,0x3f553f35,0x3f553f35,0x3f0e3f35,0xbe48bec4,0x3f7b3f6d,0x3f7b3f6d,0x3e483ec4,
0xbe950000,0xbf75bf80,0xbef1bf35,0x3f623f35,0xbf46bf0e,0xbf22bf55,0x3dc9be48,0x3f7f3f7b,0xbf7fbf6d,0xbdc9bec4,0x3f223ec4,0x3f463f6d,
0xbf62bf7b,0x3ef13e48,0x3f753f55,0x3e953f0e,0x3f6d3f80,0xbec48000,0xbf6dbf80,0x3ec48000,0x3ec43f35,0xbf6dbf35,0xbec4bf35,0x3f6d3f35,
0xbec40000,0xbf6dbf80,0x3ec40000,0x3f6d3f80,0xbf6dbf35,0xbec4bf35,0x3f6d3f35,0x3ec43f35,0x3ef10000,0x3f623f80,0xbf75bf35,0xbe95bf35,
0x3f7f3f55,0x3dc93f0e,0xbf46bf7b,0x3f223e48,0x3f223f6d,0xbf46bec4,0x3dc9bec4,0x3f7f3f6d,0xbe953e48,0xbf75bf7b,0x3f623f0e,0x3ef13f55,
0xbf55bf80,0x3f0e8000,0xbf0e0000,0xbf55bf80,0x3e48bec4,0x3f7b3f6d,0xbf7bbf6d,0x3e48bec4,0x3f7b3f35,0x3e483f35,0xbe48bf35,0x3f7b3f35,
0x3f0e3f6d,0xbf55bec4,0x3f553ec4,0x3f0e3f6d,0xbf220000,0xbf46bf80,0x3dc93f35,0xbf7fbf35,0xbf62bf7b,0x3ef1be48,0xbf75bf0e,0xbe95bf55,
0x3e95bec4,0x3f753f6d,0xbef1bf6d,0x3f623ec4,0x3f7f3f55,0xbdc93f0e,0x3f463e48,0x3f223f7b,0x3f353f80,0xbf358000,0x3f353f80,0xbf358000,
0xbf350000,0xbf35bf80,0xbf350000,0xbf35bf80,0xbf35bf80,0x3f358000,0xbf35bf80,0x3f358000,0x3f350000,0x3f353f80,0x3f350000,0x3f353f80,
0x3f460000,0x3f223f80,0x3f7f3f35,0xbdc93f35,0x3ef13f7b,0xbf62be48,0xbe953f0e,0xbf75bf55,0xbf75bec4,0xbe95bf6d,0xbf62bf6d,0x3ef1bec4,
0xbdc9bf55,0x3f7f3f0e,0x3f22be48,0x3f463f7b,0xbf0ebf80,0x3f558000,0x3f550000,0x3f0e3f80,0x3f7b3ec4,0x3e483f6d,0x3e483f6d,0xbf7bbec4,
0xbe483f35,0xbf7bbf35,0xbf7bbf35,0x3e48bf35,0xbf55bf6d,0x3f0ebec4,0x3f0ebec4,0x3f553f6d,0xbf620000,0xbef1bf80,0x3e95bf35,0x3f753f35,
0x3dc9bf55,0x3f7f3f0e,0x3f223f7b,0xbf463e48,0x3f463f6d,0xbf223ec4,0xbf7fbec4,0xbdc9bf6d,0xbf75be48,0xbe95bf7b,0x3ef1bf0e,0x3f623f55,
0x3ec43f80,0xbf6d8000,0xbec4bf80,0x3f6d8000,0xbf6dbf35,0x3ec4bf35,0x3f6d3f35,0xbec43f35,0x3f6d0000,0x3ec43f80,0xbf6d0000,0xbec4bf80,
0xbec43f35,0xbf6dbf35,0x3ec4bf35,0x3f6d3f35,0x3f750000,0x3e953f80,0xbf62bf35,0x3ef1bf35,0xbf223f0e,0xbf46bf55,0x3f7f3e48,0x3dc93f7b,
0x3dc9bf6d,0x3f7f3ec4,0xbf463ec4,0xbf22bf6d,0x3ef13f7b,0xbf623e48,0x3e95bf55,0x3f753f0e,0xbe48bf80,0x3f7b8000,0xbf7b0000,0xbe48bf80,
0x3f0e3f6d,0xbf553ec4,0x3f55bec4,0x3f0e3f6d,0xbf55bf35,0x3f0ebf35,0xbf0e3f35,0xbf55bf35,0x3f7b3ec4,0xbe483f6d,0x3e48bf6d,0x3f7b3ec4,
0xbf7f0000,0xbdc9bf80,0xbf223f35,0xbf46bf35,0x3f75be48,0x3e953f7b,0x3ef1bf55,0x3f623f0e,0xbf623ec4,0xbef1bf6d,0xbe953f6d,0xbf75bec4,
0x3f46bf0e,0x3f223f55,0x3dc9bf7b,0x3f7f3e48,0x3f80,0xbf808000,0x3f80,0xbf808000,0xbf80,0x3f808000,0xbf80,0x3f808000,
0x3f80,0xbf808000,0x3f80,0xbf808000,0xbf80,0x3f808000,0xbf80,0x3f808000,0x3f7f0000,0xbdc93f80,0x3f223f35,0xbf463f35,
0xbf75be48,0x3e95bf7b,0xbef1bf55,0x3f62bf0e,0x3f623ec4,0xbef13f6d,0x3e953f6d,0xbf753ec4,0xbf46bf0e,0x3f22bf55,0xbdc9bf7b,0x3f7fbe48,
0x3e48bf80,0x3f7b8000,0x3f7b0000,0xbe483f80,0xbf0e3f6d,0xbf55bec4,0xbf55bec4,0x3f0ebf6d,0x3f55bf35,0x3f0e3f35,0x3f0e3f35,0xbf553f35,
0xbf7b3ec4,0xbe48bf6d,0xbe48bf6d,0x3f7bbec4,0xbf750000,0x3e95bf80,0x3f62bf35,0x3ef13f35,0x3f223f0e,0xbf463f55,0xbf7f3e48,0x3dc9bf7b,
0xbdc9bf6d,0x3f7fbec4,0x3f463ec4,0xbf223f6d,0xbef13f7b,0xbf62be48,0xbe95bf55,0x3f75bf0e,0xbec43f80,0xbf6d8000,0x3ec4bf80,0x3f6d8000,
0x3f6dbf35,0x3ec43f35,0xbf6d3f35,0xbec4bf35,0xbf6d0000,0x3ec4bf80,0x3f6d0000,0xbec43f80,0x3ec43f35,0xbf6d3f35,0xbec4bf35,0x3f6dbf35,
0x3f620000,0xbef13f80,0xbe95bf35,0x3f75bf35,0xbdc9bf55,0x3f7fbf0e,0xbf223f7b,0xbf46be48,0xbf463f6d,0xbf22bec4,0x3f7fbec4,0xbdc93f6d,
0x3f75be48,0xbe953f7b,0xbef1bf0e,0x3f62bf55,0x3f0ebf80,0x3f558000,0xbf550000,0x3f0ebf80,0xbf7b3ec4,0x3e48bf6d,0xbe483f6d,0xbf7b3ec4,
0x3e483f35,0xbf7b3f35,0x3f7bbf35,0x3e483f35,0x3f55bf6d,0x3f0e3ec4,0xbf0ebec4,0x3f55bf6d,0xbf460000,0x3f22bf80,0xbf7f3f35,0xbdc9bf35,
0xbef13f7b,0xbf623e48,0x3e953f0e,0xbf753f55,0x3f75bec4,0xbe953f6d,0x3f62bf6d,0x3ef13ec4,0x3dc9bf55,0x3f7fbf0e,0xbf22be48,0x3f46bf7b,
0xbf353f80,0xbf358000,0xbf353f80,0xbf358000,0x3f350000,0xbf353f80,0x3f350000,0xbf353f80,0x3f35bf80,0x3f358000,0x3f35bf80,0x3f358000,
0xbf350000,0x3f35bf80,0xbf350000,0x3f35bf80,0x3f220000,0xbf463f80,0xbdc93f35,0xbf7f3f35,0x3f62bf7b,0x3ef13e48,0x3f75bf0e,0xbe953f55,
0xbe95bec4,0x3f75bf6d,0x3ef1bf6d,0x3f62bec4,0xbf7f3f55,0xbdc9bf0e,0xbf463e48,0x3f22bf7b,0x3f55bf80,0x3f0e8000,0x3f0e0000,0xbf553f80,
0xbe48bec4,0x3f7bbf6d,0x3f7bbf6d,0x3e483ec4,0xbf7b3f35,0x3e48bf35,0x3e48bf35,0x3f7bbf35,0xbf0e3f6d,0xbf553ec4,0xbf553ec4,0x3f0ebf6d,
0xbef10000,0x3f62bf80,0x3f75bf35,0xbe953f35,0xbf7f3f55,0x3dc9bf0e,0x3f46bf7b,0x3f22be48,0xbf223f6d,0xbf463ec4,0xbdc9bec4,0x3f7fbf6d,
0x3e953e48,0xbf753f7b,0xbf623f0e,0x3ef1bf55,0xbf6d3f80,0xbec48000,0x3f6dbf80,0x3ec48000,0xbec43f35,0xbf6d3f35,0x3ec4bf35,0x3f6dbf35,
0x3ec40000,0xbf6d3f80,0xbec40000,0x3f6dbf80,0x3f6dbf35,0xbec43f35,0xbf6d3f35,0x3ec4bf35,0x3e950000,0xbf753f80,0x3ef1bf35,0x3f62bf35,
0x3f46bf0e,0xbf223f55,0xbdc9be48,0x3f7fbf7b,0x3f7fbf6d,0xbdc93ec4,0xbf223ec4,0x3f46bf6d,0x3f62bf7b,0x3ef1be48,0xbf753f55,0x3e95bf0e,
0x3f7bbf80,0x3e488000,0xbe480000,0x3f7bbf80,0x3f55bf6d,0x3f0ebec4,0xbf0e3ec4,0x3f55bf6d,0x3f0ebf35,0x3f55bf35,0xbf553f35,0x3f0ebf35,
0x3e48bec4,0x3f7bbf6d,0xbf7b3f6d,0x3e48bec4,0xbdc90000,0x3f7fbf80,0xbf463f35,0x3f22bf35,0xbe953e48,0x3f75bf7b,0xbf623f55,0x3ef1bf0e,
0xbef13ec4,0x3f62bf6d,0xbf753f6d,0x3e95bec4,0xbf223f0e,0x3f46bf55,0xbf7f3f7b,0x3dc9be48,0x3f803f80,0x3f803f80,0x3f803f80,0x3f803f80,
0x3f803f80,0x3f803f80,0x3f803f80,0x3f803f80,0x3f803f80,0x3f803f80,0x3f803f80,0x3f803f80,0x3f803f80,0x3f803f80,0x3f803f80,0x3f803f80,
0x0,0x0,0x0,0x0,0x0,0x0,0x0,0x0,0x0,0x0,0x0,0x0,
0x0,0x0,0x0,0x0,0xbe480000,0xbf0ebec4,0xbf55bf35,0xbf7bbf6d,0x3f7b3f80,0x3f553f6d,0x3f0e3f35,0x3e483ec4,
0x3e480000,0x3f0e3ec4,0x3f553f35,0x3f7b3f6d,0xbf7bbf80,0xbf55bf6d,0xbf0ebf35,0xbe48bec4,0x3f7b3f80,0x3f553f6d,0x3f0e3f35,0x3e483ec4,
0x3e480000,0x3f0e3ec4,0x3f553f35,0x3f7b3f6d,0xbf7bbf80,0xbf55bf6d,0xbf0ebf35,0xbe48bec4,0xbe480000,0xbf0ebec4,0xbf55bf35,0xbf7bbf6d,
0x3f6d3f80,0x3ec43f35,0xbec40000,0xbf6dbf35,0xbf6dbf80,0xbec4bf35,0x3ec40000,0x3f6d3f35,0x3f6d3f80,0x3ec43f35,0xbec40000,0xbf6dbf35,
0xbf6dbf80,0xbec4bf35,0x3ec40000,0x3f6d3f35,0x3ec40000,0x3f6d3f35,0x3f6d3f80,0x3ec43f35,0xbec40000,0xbf6dbf35,0xbf6dbf80,0xbec4bf35,
0x3ec40000,0x3f6d3f35,0x3f6d3f80,0x3ec43f35,0xbec40000,0xbf6dbf35,0xbf6dbf80,0xbec4bf35,0xbf0e0000,0xbf7bbf6d,0xbe48bf35,0x3f553ec4,
0xbf55bf80,0x3e48bec4,0x3f7b3f35,0x3f0e3f6d,0x3f0e0000,0x3f7b3f6d,0x3e483f35,0xbf55bec4,0x3f553f80,0xbe483ec4,0xbf7bbf35,0xbf0ebf6d,
0x3f553f80,0xbe483ec4,0xbf7bbf35,0xbf0ebf6d,0xbf0e0000,0xbf7bbf6d,0xbe48bf35,0x3f553ec4,0xbf55bf80,0x3e48bec4,0x3f7b3f35,0x3f0e3f6d,
0x3f0e0000,0x3f7b3f6d,0x3e483f35,0xbf55bec4,0x3f350000,0x3f353f80,0xbf350000,0xbf35bf80,0x3f350000,0x3f353f80,0xbf350000,0xbf35bf80,
0x3f350000,0x3f353f80,0xbf350000,0xbf35bf80,0x3f350000,0x3f353f80,0xbf350000,0xbf35bf80,0x3f353f80,0xbf350000,0xbf35bf80,0x3f350000,
0x3f353f80,0xbf350000,0xbf35bf80,0x3f350000,0x3f353f80,0xbf350000,0xbf35bf80,0x3f350000,0x3f353f80,0xbf350000,0xbf35bf80,0x3f350000,
0x3f0e3f80,0xbf7bbec4,0x3e48bf35,0x3f553f6d,0x3f550000,0x3e483f6d,0xbf7bbf35,0x3f0ebec4,0xbf0ebf80,0x3f7b3ec4,0xbe483f35,0xbf55bf6d,
0xbf550000,0xbe48bf6d,0x3f7b3f35,0xbf0e3ec4,0xbf550000,0xbe48bf6d,0x3f7b3f35,0xbf0e3ec4,0x3f0e3f80,0xbf7bbec4,0x3e48bf35,0x3f553f6d,
0x3f550000,0x3e483f6d,0xbf7bbf35,0x3f0ebec4,0xbf0ebf80,0x3f7b3ec4,0xbe483f35,0xbf55bf6d,0x3f6d0000,0xbec43f35,0xbec4bf80,0x3f6d3f35,
0xbf6d0000,0x3ec4bf35,0x3ec43f80,0xbf6dbf35,0x3f6d0000,0xbec43f35,0xbec4bf80,0x3f6d3f35,0xbf6d0000,0x3ec4bf35,0x3ec43f80,0xbf6dbf35,
0x3ec43f80,0xbf6dbf35,0x3f6d0000,0xbec43f35,0xbec4bf80,0x3f6d3f35,0xbf6d0000,0x3ec4bf35,0x3ec43f80,0xbf6dbf35,0x3f6d0000,0xbec43f35,
0xbec4bf80,0x3f6d3f35,0xbf6d0000,0x3ec4bf35,0x3e483f80,0xbf0ebf6d,0x3f553f35,0xbf7bbec4,0xbf7b0000,0x3f55bec4,0xbf0e3f35,0x3e48bf6d,
0xbe48bf80,0x3f0e3f6d,0xbf55bf35,0x3f7b3ec4,0x3f7b0000,0xbf553ec4,0x3f0ebf35,0xbe483f6d,0xbf7b0000,0x3f55bec4,0xbf0e3f35,0x3e48bf6d,
0xbe48bf80,0x3f0e3f6d,0xbf55bf35,0x3f7b3ec4,0x3f7b0000,0xbf553ec4,0x3f0ebf35,0xbe483f6d,0x3e483f80,0xbf0ebf6d,0x3f553f35,0xbf7bbec4,
0x3f80,0xbf80,0x3f80,0xbf80,0x3f80,0xbf80,0x3f80,0xbf80,0x3f80,0xbf80,0x3f80,0xbf80,
0x3f80,0xbf80,0x3f80,0xbf80,0x3f800000,0xbf800000,0x3f800000,0xbf800000,0x3f800000,0xbf800000,0x3f800000,0xbf800000,
0x3f800000,0xbf800000,0x3f800000,0xbf800000,0x3f800000,0xbf800000,0x3f800000,0xbf800000,0xbf7b0000,0x3f553ec4,0xbf0ebf35,0x3e483f6d,
0xbe483f80,0x3f0ebf6d,0xbf553f35,0x3f7bbec4,0x3f7b0000,0xbf55bec4,0x3f0e3f35,0xbe48bf6d,0x3e48bf80,0xbf0e3f6d,0x3f55bf35,0xbf7b3ec4,
0xbe483f80,0x3f0ebf6d,0xbf553f35,0x3f7bbec4,0x3f7b0000,0xbf55bec4,0x3f0e3f35,0xbe48bf6d,0x3e48bf80,0xbf0e3f6d,0x3f55bf35,0xbf7b3ec4,
0xbf7b0000,0x3f553ec4,0xbf0ebf35,0x3e483f6d,0xbec43f80,0x3f6dbf35,0xbf6d0000,0x3ec43f35,0x3ec4bf80,0xbf6d3f35,0x3f6d0000,0xbec4bf35,
0xbec43f80,0x3f6dbf35,0xbf6d0000,0x3ec43f35,0x3ec4bf80,0xbf6d3f35,0x3f6d0000,0xbec4bf35,0x3f6d0000,0xbec4bf35,0xbec43f80,0x3f6dbf35,
0xbf6d0000,0x3ec43f35,0x3ec4bf80,0xbf6d3f35,0x3f6d0000,0xbec4bf35,0xbec43f80,0x3f6dbf35,0xbf6d0000,0x3ec43f35,0x3ec4bf80,0xbf6d3f35,
0xbf550000,0xbe483f6d,0x3f7bbf35,0xbf0ebec4,0x3f0ebf80,0xbf7b3ec4,0x3e483f35,0x3f55bf6d,0x3f550000,0x3e48bf6d,0xbf7b3f35,0x3f0e3ec4,
0xbf0e3f80,0x3f7bbec4,0xbe48bf35,0xbf553f6d,0xbf0e3f80,0x3f7bbec4,0xbe48bf35,0xbf553f6d,0xbf550000,0xbe483f6d,0x3f7bbf35,0xbf0ebec4,
0x3f0ebf80,0xbf7b3ec4,0x3e483f35,0x3f55bf6d,0x3f550000,0x3e48bf6d,0xbf7b3f35,0x3f0e3ec4,0x3f350000,0x3f35bf80,0xbf350000,0xbf353f80,
0x3f350000,0x3f35bf80,0xbf350000,0xbf353f80,0x3f350000,0x3f35bf80,0xbf350000,0xbf353f80,0x3f350000,0x3f35bf80,0xbf350000,0xbf353f80,
0xbf353f80,0x3f350000,0x3f35bf80,0xbf350000,0xbf353f80,0x3f350000,0x3f35bf80,0xbf350000,0xbf353f80,0x3f350000,0x3f35bf80,0xbf350000,
0xbf353f80,0x3f350000,0x3f35bf80,0xbf350000,0xbf553f80,0x3e483ec4,0x3f7bbf35,0x3f0ebf6d,0x3f0e0000,0x3f7bbf6d,0x3e48bf35,0xbf553ec4,
0x3f55bf80,0xbe48bec4,0xbf7b3f35,0xbf0e3f6d,0xbf0e0000,0xbf7b3f6d,0xbe483f35,0x3f55bec4,0xbf0e0000,0xbf7b3f6d,0xbe483f35,0x3f55bec4,
0xbf553f80,0x3e483ec4,0x3f7bbf35,0x3f0ebf6d,0x3f0e0000,0x3f7bbf6d,0x3e48bf35,0xbf553ec4,0x3f55bf80,0xbe48bec4,0xbf7b3f35,0xbf0e3f6d,
0x3ec40000,0x3f6dbf35,0x3f6dbf80,0x3ec4bf35,0xbec40000,0xbf6d3f35,0xbf6d3f80,0xbec43f35,0x3ec40000,0x3f6dbf35,0x3f6dbf80,0x3ec4bf35,
0xbec40000,0xbf6d3f35,0xbf6d3f80,0xbec43f35,0xbf6d3f80,0xbec43f35,0x3ec40000,0x3f6dbf35,0x3f6dbf80,0x3ec4bf35,0xbec40000,0xbf6d3f35,
0xbf6d3f80,0xbec43f35,0x3ec40000,0x3f6dbf35,0x3f6dbf80,0x3ec4bf35,0xbec40000,0xbf6d3f35,0xbf7b3f80,0xbf553f6d,0xbf0e3f35,0xbe483ec4,
0xbe480000,0xbf0e3ec4,0xbf553f35,0xbf7b3f6d,0x3f7bbf80,0x3f55bf6d,0x3f0ebf35,0x3e48bec4,0x3e480000,0x3f0ebec4,0x3f55bf35,0x3f7bbf6d,
0xbe480000,0xbf0e3ec4,0xbf553f35,0xbf7b3f6d,0x3f7bbf80,0x3f55bf6d,0x3f0ebf35,0x3e48bec4,0x3e480000,0x3f0ebec4,0x3f55bf35,0x3f7bbf6d,
0xbf7b3f80,0xbf553f6d,0xbf0e3f35,0xbe483ec4,0xbf803f80,0xbf803f80,0xbf803f80,0xbf803f80,0xbf803f80,0xbf803f80,0xbf803f80,0xbf803f80,
0xbf803f80,0xbf803f80,0xbf803f80,0xbf803f80,0xbf803f80,0xbf803f80,0xbf803f80,0xbf803f80,0x0,0x0,0x0,0x0,
0x0,0x0,0x0,0x0,0x0,0x0,0x0,0x0,0x0,0x0,0x0,0x0,
0x3e480000,0x3f0ebec4,0x3f55bf35,0x3f7bbf6d,0xbf7b3f80,0xbf553f6d,0xbf0e3f35,0xbe483ec4,0xbe480000,0xbf0e3ec4,0xbf553f35,0xbf7b3f6d,
0x3f7bbf80,0x3f55bf6d,0x3f0ebf35,0x3e48bec4,0xbf7b3f80,0xbf553f6d,0xbf0e3f35,0xbe483ec4,0xbe480000,0xbf0e3ec4,0xbf553f35,0xbf7b3f6d,
0x3f7bbf80,0x3f55bf6d,0x3f0ebf35,0x3e48bec4,0x3e480000,0x3f0ebec4,0x3f55bf35,0x3f7bbf6d,0xbf6d3f80,0xbec43f35,0x3ec40000,0x3f6dbf35,
0x3f6dbf80,0x3ec4bf35,0xbec40000,0xbf6d3f35,0xbf6d3f80,0xbec43f35,0x3ec40000,0x3f6dbf35,0x3f6dbf80,0x3ec4bf35,0xbec40000,0xbf6d3f35,
0xbec40000,0xbf6d3f35,0xbf6d3f80,0xbec43f35,0x3ec40000,0x3f6dbf35,0x3f6dbf80,0x3ec4bf35,0xbec40000,0xbf6d3f35,0xbf6d3f80,0xbec43f35,
0x3ec40000,0x3f6dbf35,0x3f6dbf80,0x3ec4bf35,0x3f0e0000,0x3f7bbf6d,0x3e48bf35,0xbf553ec4,0x3f55bf80,0xbe48bec4,0xbf7b3f35,0xbf0e3f6d,
0xbf0e0000,0xbf7b3f6d,0xbe483f35,0x3f55bec4,0xbf553f80,0x3e483ec4,0x3f7bbf35,0x3f0ebf6d,0xbf553f80,0x3e483ec4,0x3f7bbf35,0x3f0ebf6d,
0x3f0e0000,0x3f7bbf6d,0x3e48bf35,0xbf553ec4,0x3f55bf80,0xbe48bec4,0xbf7b3f35,0xbf0e3f6d,0xbf0e0000,0xbf7b3f6d,0xbe483f35,0x3f55bec4,
0xbf350000,0xbf353f80,0x3f350000,0x3f35bf80,0xbf350000,0xbf353f80,0x3f350000,0x3f35bf80,0xbf350000,0xbf353f80,0x3f350000,0x3f35bf80,
0xbf350000,0xbf353f80,0x3f350000,0x3f35bf80,0xbf353f80,0x3f350000,0x3f35bf80,0xbf350000,0xbf353f80,0x3f350000,0x3f35bf80,0xbf350000,
0xbf353f80,0x3f350000,0x3f35bf80,0xbf350000,0xbf353f80,0x3f350000,0x3f35bf80,0xbf350000,0xbf0e3f80,0x3f7bbec4,0xbe48bf35,0xbf553f6d,
0xbf550000,0xbe483f6d,0x3f7bbf35,0xbf0ebec4,0x3f0ebf80,0xbf7b3ec4,0x3e483f35,0x3f55bf6d,0x3f550000,0x3e48bf6d,0xbf7b3f35,0x3f0e3ec4,
0x3f550000,0x3e48bf6d,0xbf7b3f35,0x3f0e3ec4,0xbf0e3f80,0x3f7bbec4,0xbe48bf35,0xbf553f6d,0xbf550000,0xbe483f6d,0x3f7bbf35,0xbf0ebec4,
0x3f0ebf80,0xbf7b3ec4,0x3e483f35,0x3f55bf6d,0xbf6d0000,0x3ec43f35,0x3ec4bf80,0xbf6d3f35,0x3f6d0000,0xbec4bf35,0xbec43f80,0x3f6dbf35,
0xbf6d0000,0x3ec43f35,0x3ec4bf80,0xbf6d3f35,0x3f6d0000,0xbec4bf35,0xbec43f80,0x3f6dbf35,0xbec43f80,0x3f6dbf35,0xbf6d0000,0x3ec43f35,
0x3ec4bf80,0xbf6d3f35,0x3f6d0000,0xbec4bf35,0xbec43f80,0x3f6dbf35,0xbf6d0000,0x3ec43f35,0x3ec4bf80,0xbf6d3f35,0x3f6d0000,0xbec4bf35,
0xbe483f80,0x3f0ebf6d,0xbf553f35,0x3f7bbec4,0x3f7b0000,0xbf55bec4,0x3f0e3f35,0xbe48bf6d,0x3e48bf80,0xbf0e3f6d,0x3f55bf35,0xbf7b3ec4,
0xbf7b0000,0x3f553ec4,0xbf0ebf35,0x3e483f6d,0x3f7b0000,0xbf55bec4,0x3f0e3f35,0xbe48bf6d,0x3e48bf80,0xbf0e3f6d,0x3f55bf35,0xbf7b3ec4,
0xbf7b0000,0x3f553ec4,0xbf0ebf35,0x3e483f6d,0xbe483f80,0x3f0ebf6d,0xbf553f35,0x3f7bbec4,0x3f80,0xbf80,0x3f80,0xbf80,
0x3f80,0xbf80,0x3f80,0xbf80,0x3f80,0xbf80,0x3f80,0xbf80,0x3f80,0xbf80,0x3f80,0xbf80,
0xbf800000,0x3f800000,0xbf800000,0x3f800000,0xbf800000,0x3f800000,0xbf800000,0x3f800000,0xbf800000,0x3f800000,0xbf800000,0x3f800000,
0xbf800000,0x3f800000,0xbf800000,0x3f800000,0x3f7b0000,0xbf553ec4,0x3f0ebf35,0xbe483f6d,0x3e483f80,0xbf0ebf6d,0x3f553f35,0xbf7bbec4,
0xbf7b0000,0x3f55bec4,0xbf0e3f35,0x3e48bf6d,0xbe48bf80,0x3f0e3f6d,0xbf55bf35,0x3f7b3ec4,0x3e483f80,0xbf0ebf6d,0x3f553f35,0xbf7bbec4,
0xbf7b0000,0x3f55bec4,0xbf0e3f35,0x3e48bf6d,0xbe48bf80,0x3f0e3f6d,0xbf55bf35,0x3f7b3ec4,0x3f7b0000,0xbf553ec4,0x3f0ebf35,0xbe483f6d,
0x3ec43f80,0xbf6dbf35,0x3f6d0000,0xbec43f35,0xbec4bf80,0x3f6d3f35,0xbf6d0000,0x3ec4bf35,0x3ec43f80,0xbf6dbf35,0x3f6d0000,0xbec43f35,
0xbec4bf80,0x3f6d3f35,0xbf6d0000,0x3ec4bf35,0xbf6d0000,0x3ec4bf35,0x3ec43f80,0xbf6dbf35,0x3f6d0000,0xbec43f35,0xbec4bf80,0x3f6d3f35,
0xbf6d0000,0x3ec4bf35,0x3ec43f80,0xbf6dbf35,0x3f6d0000,0xbec43f35,0xbec4bf80,0x3f6d3f35,0x3f550000,0x3e483f6d,0xbf7bbf35,0x3f0ebec4,
0xbf0ebf80,0x3f7b3ec4,0xbe483f35,0xbf55bf6d,0xbf550000,0xbe48bf6d,0x3f7b3f35,0xbf0e3ec4,0x3f0e3f80,0xbf7bbec4,0x3e48bf35,0x3f553f6d,
0x3f0e3f80,0xbf7bbec4,0x3e48bf35,0x3f553f6d,0x3f550000,0x3e483f6d,0xbf7bbf35,0x3f0ebec4,0xbf0ebf80,0x3f7b3ec4,0xbe483f35,0xbf55bf6d,
0xbf550000,0xbe48bf6d,0x3f7b3f35,0xbf0e3ec4,0xbf350000,0xbf35bf80,0x3f350000,0x3f353f80,0xbf350000,0xbf35bf80,0x3f350000,0x3f353f80,
0xbf350000,0xbf35bf80,0x3f350000,0x3f353f80,0xbf350000,0xbf35bf80,0x3f350000,0x3f353f80,0x3f353f80,0xbf350000,0xbf35bf80,0x3f350000,
0x3f353f80,0xbf350000,0xbf35bf80,0x3f350000,0x3f353f80,0xbf350000,0xbf35bf80,0x3f350000,0x3f353f80,0xbf350000,0xbf35bf80,0x3f350000,
0x3f553f80,0xbe483ec4,0xbf7bbf35,0xbf0ebf6d,0xbf0e0000,0xbf7bbf6d,0xbe48bf35,0x3f553ec4,0xbf55bf80,0x3e48bec4,0x3f7b3f35,0x3f0e3f6d,
0x3f0e0000,0x3f7b3f6d,0x3e483f35,0xbf55bec4,0x3f0e0000,0x3f7b3f6d,0x3e483f35,0xbf55bec4,0x3f553f80,0xbe483ec4,0xbf7bbf35,0xbf0ebf6d,
0xbf0e0000,0xbf7bbf6d,0xbe48bf35,0x3f553ec4,0xbf55bf80,0x3e48bec4,0x3f7b3f35,0x3f0e3f6d,0xbec40000,0xbf6dbf35,0xbf6dbf80,0xbec4bf35,
0x3ec40000,0x3f6d3f35,0x3f6d3f80,0x3ec43f35,0xbec40000,0xbf6dbf35,0xbf6dbf80,0xbec4bf35,0x3ec40000,0x3f6d3f35,0x3f6d3f80,0x3ec43f35,
0x3f6d3f80,0x3ec43f35,0xbec40000,0xbf6dbf35,0xbf6dbf80,0xbec4bf35,0x3ec40000,0x3f6d3f35,0x3f6d3f80,0x3ec43f35,0xbec40000,0xbf6dbf35,
0xbf6dbf80,0xbec4bf35,0x3ec40000,0x3f6d3f35,0x3f7b3f80,0x3f553f6d,0x3f0e3f35,0x3e483ec4,0x3e480000,0x3f0e3ec4,0x3f553f35,0x3f7b3f6d,
0xbf7bbf80,0xbf55bf6d,0xbf0ebf35,0xbe48bec4,0xbe480000,0xbf0ebec4,0xbf55bf35,0xbf7bbf6d,0x3e480000,0x3f0e3ec4,0x3f553f35,0x3f7b3f6d,
0xbf7bbf80,0xbf55bf6d,0xbf0ebf35,0xbe48bec4,0xbe480000,0xbf0ebec4,0xbf55bf35,0xbf7bbf6d,0x3f7b3f80,0x3f553f6d,0x3f0e3f35,0x3e483ec4,
0x80008000,0x80008000,0x80008000,0x80008000,0x80008000,0x80008000,0x80008000,0x80008000,0x80008000,0x80008000,0x80008000,0x80008000,
0x80008000,0x80008000,0x80008000,0x80008000,0x3f803f80,0x3f803f80,0x3f803f80,0x3f803f80,0x3f803f80,0x3f803f80,0x3f803f80,0x3f803f80,
0x3f803f80,0x3f803f80,0x3f803f80,0x3f803f80,0x3f803f80,0x3f803f80,0x3f803f80,0x3f803f80,0xbf7bbf80,0xbf55bf6d,0xbf0ebf35,0xbe48bec4,
0xbe488000,0xbf0ebec4,0xbf55bf35,0xbf7bbf6d,0x3f7b3f80,0x3f553f6d,0x3f0e3f35,0x3e483ec4,0x3e488000,0x3f0e3ec4,0x3f553f35,0x3f7b3f6d,
0xbe480000,0xbf0ebec4,0xbf55bf35,0xbf7bbf6d,0x3f7b3f80,0x3f553f6d,0x3f0e3f35,0x3e483ec4,0x3e480000,0x3f0e3ec4,0x3f553f35,0x3f7b3f6d,
0xbf7bbf80,0xbf55bf6d,0xbf0ebf35,0xbe48bec4,0xbec48000,0xbf6dbf35,0xbf6dbf80,0xbec4bf35,0x3ec48000,0x3f6d3f35,0x3f6d3f80,0x3ec43f35,
0xbec48000,0xbf6dbf35,0xbf6dbf80,0xbec4bf35,0x3ec48000,0x3f6d3f35,0x3f6d3f80,0x3ec43f35,0x3f6d3f80,0x3ec43f35,0xbec40000,0xbf6dbf35,
0xbf6dbf80,0xbec4bf35,0x3ec40000,0x3f6d3f35,0x3f6d3f80,0x3ec43f35,0xbec40000,0xbf6dbf35,0xbf6dbf80,0xbec4bf35,0x3ec40000,0x3f6d3f35,
0xbf55bf80,0x3e48bec4,0x3f7b3f35,0x3f0e3f6d,0x3f0e8000,0x3f7b3f6d,0x3e483f35,0xbf55bec4,0x3f553f80,0xbe483ec4,0xbf7bbf35,0xbf0ebf6d,
0xbf0e8000,0xbf7bbf6d,0xbe48bf35,0x3f553ec4,0xbf0e0000,0xbf7bbf6d,0xbe48bf35,0x3f553ec4,0xbf55bf80,0x3e48bec4,0x3f7b3f35,0x3f0e3f6d,
0x3f0e0000,0x3f7b3f6d,0x3e483f35,0xbf55bec4,0x3f553f80,0xbe483ec4,0xbf7bbf35,0xbf0ebf6d,0x3f353f80,0xbf350000,0xbf35bf80,0x3f350000,
0x3f353f80,0xbf350000,0xbf35bf80,0x3f350000,0x3f353f80,0xbf350000,0xbf35bf80,0x3f350000,0x3f353f80,0xbf350000,0xbf35bf80,0x3f350000,
0xbf358000,0xbf35bf80,0x3f358000,0x3f353f80,0xbf358000,0xbf35bf80,0x3f358000,0x3f353f80,0xbf358000,0xbf35bf80,0x3f358000,0x3f353f80,
0xbf358000,0xbf35bf80,0x3f358000,0x3f353f80,0xbf550000,0xbe48bf6d,0x3f7b3f35,0xbf0e3ec4,0x3f0e3f80,0xbf7bbec4,0x3e48bf35,0x3f553f6d,
0x3f550000,0x3e483f6d,0xbf7bbf35,0x3f0ebec4,0xbf0ebf80,0x3f7b3ec4,0xbe483f35,0xbf55bf6d,0xbf0ebf80,0x3f7b3ec4,0xbe483f35,0xbf55bf6d,
0xbf558000,0xbe48bf6d,0x3f7b3f35,0xbf0e3ec4,0x3f0e3f80,0xbf7bbec4,0x3e48bf35,0x3f553f6d,0x3f558000,0x3e483f6d,0xbf7bbf35,0x3f0ebec4,
0x3ec43f80,0xbf6dbf35,0x3f6d0000,0xbec43f35,0xbec4bf80,0x3f6d3f35,0xbf6d0000,0x3ec4bf35,0x3ec43f80,0xbf6dbf35,0x3f6d0000,0xbec43f35,
0xbec4bf80,0x3f6d3f35,0xbf6d0000,0x3ec4bf35,0xbf6d8000,0x3ec4bf35,0x3ec43f80,0xbf6dbf35,0x3f6d8000,0xbec43f35,0xbec4bf80,0x3f6d3f35,
0xbf6d8000,0x3ec4bf35,0x3ec43f80,0xbf6dbf35,0x3f6d8000,0xbec43f35,0xbec4bf80,0x3f6d3f35,0xbf7b0000,0x3f55bec4,0xbf0e3f35,0x3e48bf6d,
0xbe48bf80,0x3f0e3f6d,0xbf55bf35,0x3f7b3ec4,0x3f7b0000,0xbf553ec4,0x3f0ebf35,0xbe483f6d,0x3e483f80,0xbf0ebf6d,0x3f553f35,0xbf7bbec4,
0xbe48bf80,0x3f0e3f6d,0xbf55bf35,0x3f7b3ec4,0x3f7b8000,0xbf553ec4,0x3f0ebf35,0xbe483f6d,0x3e483f80,0xbf0ebf6d,0x3f553f35,0xbf7bbec4,
0xbf7b8000,0x3f55bec4,0xbf0e3f35,0x3e48bf6d,0xbf808000,0x3f808000,0xbf808000,0x3f808000,0xbf808000,0x3f808000,0xbf808000,0x3f808000,
0xbf808000,0x3f808000,0xbf808000,0x3f808000,0xbf808000,0x3f808000,0xbf808000,0x3f808000,0x3f80,0xbf80,0x3f80,0xbf80,
0x3f80,0xbf80,0x3f80,0xbf80,0x3f80,0xbf80,0x3f80,0xbf80,0x3f80,0xbf80,0x3f80,0xbf80,
0x3e48bf80,0xbf0e3f6d,0x3f55bf35,0xbf7b3ec4,0xbf7b8000,0x3f553ec4,0xbf0ebf35,0x3e483f6d,0xbe483f80,0x3f0ebf6d,0xbf553f35,0x3f7bbec4,
0x3f7b8000,0xbf55bec4,0x3f0e3f35,0xbe48bf6d,0xbf7b0000,0x3f553ec4,0xbf0ebf35,0x3e483f6d,0xbe483f80,0x3f0ebf6d,0xbf553f35,0x3f7bbec4,
0x3f7b0000,0xbf55bec4,0x3f0e3f35,0xbe48bf6d,0x3e48bf80,0xbf0e3f6d,0x3f55bf35,0xbf7b3ec4,0xbf6d8000,0x3ec43f35,0x3ec4bf80,0xbf6d3f35,
0x3f6d8000,0xbec4bf35,0xbec43f80,0x3f6dbf35,0xbf6d8000,0x3ec43f35,0x3ec4bf80,0xbf6d3f35,0x3f6d8000,0xbec4bf35,0xbec43f80,0x3f6dbf35,
0xbec43f80,0x3f6dbf35,0xbf6d0000,0x3ec43f35,0x3ec4bf80,0xbf6d3f35,0x3f6d0000,0xbec4bf35,0xbec43f80,0x3f6dbf35,0xbf6d0000,0x3ec43f35,
0x3ec4bf80,0xbf6d3f35,0x3f6d0000,0xbec4bf35,0x3f0ebf80,0xbf7b3ec4,0x3e483f35,0x3f55bf6d,0x3f558000,0x3e48bf6d,0xbf7b3f35,0x3f0e3ec4,
0xbf0e3f80,0x3f7bbec4,0xbe48bf35,0xbf553f6d,0xbf558000,0xbe483f6d,0x3f7bbf35,0xbf0ebec4,0xbf550000,0xbe483f6d,0x3f7bbf35,0xbf0ebec4,
0x3f0ebf80,0xbf7b3ec4,0x3e483f35,0x3f55bf6d,0x3f550000,0x3e48bf6d,0xbf7b3f35,0x3f0e3ec4,0xbf0e3f80,0x3f7bbec4,0xbe48bf35,0xbf553f6d,
0xbf353f80,0x3f350000,0x3f35bf80,0xbf350000,0xbf353f80,0x3f350000,0x3f35bf80,0xbf350000,0xbf353f80,0x3f350000,0x3f35bf80,0xbf350000,
0xbf353f80,0x3f350000,0x3f35bf80,0xbf350000,0xbf358000,0xbf353f80,0x3f358000,0x3f35bf80,0xbf358000,0xbf353f80,0x3f358000,0x3f35bf80,
0xbf358000,0xbf353f80,0x3f358000,0x3f35bf80,0xbf358000,0xbf353f80,0x3f358000,0x3f35bf80,0xbf0e0000,0xbf7b3f6d,0xbe483f35,0x3f55bec4,
0xbf553f80,0x3e483ec4,0x3f7bbf35,0x3f0ebf6d,0x3f0e0000,0x3f7bbf6d,0x3e48bf35,0xbf553ec4,0x3f55bf80,0xbe48bec4,0xbf7b3f35,0xbf0e3f6d,
0x3f55bf80,0xbe48bec4,0xbf7b3f35,0xbf0e3f6d,0xbf0e8000,0xbf7b3f6d,0xbe483f35,0x3f55bec4,0xbf553f80,0x3e483ec4,0x3f7bbf35,0x3f0ebf6d,
0x3f0e8000,0x3f7bbf6d,0x3e48bf35,0xbf553ec4,0xbf6d3f80,0xbec43f35,0x3ec40000,0x3f6dbf35,0x3f6dbf80,0x3ec4bf35,0xbec40000,0xbf6d3f35,
0xbf6d3f80,0xbec43f35,0x3ec40000,0x3f6dbf35,0x3f6dbf80,0x3ec4bf35,0xbec40000,0xbf6d3f35,0xbec48000,0xbf6d3f35,0xbf6d3f80,0xbec43f35,
0x3ec48000,0x3f6dbf35,0x3f6dbf80,0x3ec4bf35,0xbec48000,0xbf6d3f35,0xbf6d3f80,0xbec43f35,0x3ec48000,0x3f6dbf35,0x3f6dbf80,0x3ec4bf35,
0xbe480000,0xbf0e3ec4,0xbf553f35,0xbf7b3f6d,0x3f7bbf80,0x3f55bf6d,0x3f0ebf35,0x3e48bec4,0x3e480000,0x3f0ebec4,0x3f55bf35,0x3f7bbf6d,
0xbf7b3f80,0xbf553f6d,0xbf0e3f35,0xbe483ec4,0x3f7bbf80,0x3f55bf6d,0x3f0ebf35,0x3e48bec4,0x3e488000,0x3f0ebec4,0x3f55bf35,0x3f7bbf6d,
0xbf7b3f80,0xbf553f6d,0xbf0e3f35,0xbe483ec4,0xbe488000,0xbf0e3ec4,0xbf553f35,0xbf7b3f6d,0x80008000,0x80008000,0x80008000,0x80008000,
0x80008000,0x80008000,0x80008000,0x80008000,0x80008000,0x80008000,0x80008000,0x80008000,0x80008000,0x80008000,0x80008000,0x80008000,
0xbf803f80,0xbf803f80,0xbf803f80,0xbf803f80,0xbf803f80,0xbf803f80,0xbf803f80,0xbf803f80,0xbf803f80,0xbf803f80,0xbf803f80,0xbf803f80,
0xbf803f80,0xbf803f80,0xbf803f80,0xbf803f80,0x3f7bbf80,0x3f55bf6d,0x3f0ebf35,0x3e48bec4,0x3e488000,0x3f0ebec4,0x3f55bf35,0x3f7bbf6d,
0xbf7b3f80,0xbf553f6d,0xbf0e3f35,0xbe483ec4,0xbe488000,0xbf0e3ec4,0xbf553f35,0xbf7b3f6d,0x3e480000,0x3f0ebec4,0x3f55bf35,0x3f7bbf6d,
0xbf7b3f80,0xbf553f6d,0xbf0e3f35,0xbe483ec4,0xbe480000,0xbf0e3ec4,0xbf553f35,0xbf7b3f6d,0x3f7bbf80,0x3f55bf6d,0x3f0ebf35,0x3e48bec4,
0x3ec48000,0x3f6dbf35,0x3f6dbf80,0x3ec4bf35,0xbec48000,0xbf6d3f35,0xbf6d3f80,0xbec43f35,0x3ec48000,0x3f6dbf35,0x3f6dbf80,0x3ec4bf35,
0xbec48000,0xbf6d3f35,0xbf6d3f80,0xbec43f35,0xbf6d3f80,0xbec43f35,0x3ec40000,0x3f6dbf35,0x3f6dbf80,0x3ec4bf35,0xbec40000,0xbf6d3f35,
0xbf6d3f80,0xbec43f35,0x3ec40000,0x3f6dbf35,0x3f6dbf80,0x3ec4bf35,0xbec40000,0xbf6d3f35,0x3f55bf80,0xbe48bec4,0xbf7b3f35,0xbf0e3f6d,
0xbf0e8000,0xbf7b3f6d,0xbe483f35,0x3f55bec4,0xbf553f80,0x3e483ec4,0x3f7bbf35,0x3f0ebf6d,0x3f0e8000,0x3f7bbf6d,0x3e48bf35,0xbf553ec4,
0x3f0e0000,0x3f7bbf6d,0x3e48bf35,0xbf553ec4,0x3f55bf80,0xbe48bec4,0xbf7b3f35,0xbf0e3f6d,0xbf0e0000,0xbf7b3f6d,0xbe483f35,0x3f55bec4,
0xbf553f80,0x3e483ec4,0x3f7bbf35,0x3f0ebf6d,0xbf353f80,0x3f350000,0x3f35bf80,0xbf350000,0xbf353f80,0x3f350000,0x3f35bf80,0xbf350000,
0xbf353f80,0x3f350000,0x3f35bf80,0xbf350000,0xbf353f80,0x3f350000,0x3f35bf80,0xbf350000,0x3f358000,0x3f35bf80,0xbf358000,0xbf353f80,
0x3f358000,0x3f35bf80,0xbf358000,0xbf353f80,0x3f358000,0x3f35bf80,0xbf358000,0xbf353f80,0x3f358000,0x3f35bf80,0xbf358000,0xbf353f80,
0x3f550000,0x3e48bf6d,0xbf7b3f35,0x3f0e3ec4,0xbf0e3f80,0x3f7bbec4,0xbe48bf35,0xbf553f6d,0xbf550000,0xbe483f6d,0x3f7bbf35,0xbf0ebec4,
0x3f0ebf80,0xbf7b3ec4,0x3e483f35,0x3f55bf6d,0x3f0ebf80,0xbf7b3ec4,0x3e483f35,0x3f55bf6d,0x3f558000,0x3e48bf6d,0xbf7b3f35,0x3f0e3ec4,
0xbf0e3f80,0x3f7bbec4,0xbe48bf35,0xbf553f6d,0xbf558000,0xbe483f6d,0x3f7bbf35,0xbf0ebec4,0xbec43f80,0x3f6dbf35,0xbf6d0000,0x3ec43f35,
0x3ec4bf80,0xbf6d3f35,0x3f6d0000,0xbec4bf35,0xbec43f80,0x3f6dbf35,0xbf6d0000,0x3ec43f35,0x3ec4bf80,0xbf6d3f35,0x3f6d0000,0xbec4bf35,
0x3f6d8000,0xbec4bf35,0xbec43f80,0x3f6dbf35,0xbf6d8000,0x3ec43f35,0x3ec4bf80,0xbf6d3f35,0x3f6d8000,0xbec4bf35,0xbec43f80,0x3f6dbf35,
0xbf6d8000,0x3ec43f35,0x3ec4bf80,0xbf6d3f35,0x3f7b0000,0xbf55bec4,0x3f0e3f35,0xbe48bf6d,0x3e48bf80,0xbf0e3f6d,0x3f55bf35,0xbf7b3ec4,
0xbf7b0000,0x3f553ec4,0xbf0ebf35,0x3e483f6d,0xbe483f80,0x3f0ebf6d,0xbf553f35,0x3f7bbec4,0x3e48bf80,0xbf0e3f6d,0x3f55bf35,0xbf7b3ec4,
0xbf7b8000,0x3f553ec4,0xbf0ebf35,0x3e483f6d,0xbe483f80,0x3f0ebf6d,0xbf553f35,0x3f7bbec4,0x3f7b8000,0xbf55bec4,0x3f0e3f35,0xbe48bf6d,
0x3f808000,0xbf808000,0x3f808000,0xbf808000,0x3f808000,0xbf808000,0x3f808000,0xbf808000,0x3f808000,0xbf808000,0x3f808000,0xbf808000,
0x3f808000,0xbf808000,0x3f808000,0xbf808000,0x3f80,0xbf80,0x3f80,0xbf80,0x3f80,0xbf80,0x3f80,0xbf80,
0x3f80,0xbf80,0x3f80,0xbf80,0x3f80,0xbf80,0x3f80,0xbf80,0xbe48bf80,0x3f0e3f6d,0xbf55bf35,0x3f7b3ec4,
0x3f7b8000,0xbf553ec4,0x3f0ebf35,0xbe483f6d,0x3e483f80,0xbf0ebf6d,0x3f553f35,0xbf7bbec4,0xbf7b8000,0x3f55bec4,0xbf0e3f35,0x3e48bf6d,
0x3f7b0000,0xbf553ec4,0x3f0ebf35,0xbe483f6d,0x3e483f80,0xbf0ebf6d,0x3f553f35,0xbf7bbec4,0xbf7b0000,0x3f55bec4,0xbf0e3f35,0x3e48bf6d,
0xbe48bf80,0x3f0e3f6d,0xbf55bf35,0x3f7b3ec4,0x3f6d8000,0xbec43f35,0xbec4bf80,0x3f6d3f35,0xbf6d8000,0x3ec4bf35,0x3ec43f80,0xbf6dbf35,
0x3f6d8000,0xbec43f35,0xbec4bf80,0x3f6d3f35,0xbf6d8000,0x3ec4bf35,0x3ec43f80,0xbf6dbf35,0x3ec43f80,0xbf6dbf35,0x3f6d0000,0xbec43f35,
0xbec4bf80,0x3f6d3f35,0xbf6d0000,0x3ec4bf35,0x3ec43f80,0xbf6dbf35,0x3f6d0000,0xbec43f35,0xbec4bf80,0x3f6d3f35,0xbf6d0000,0x3ec4bf35,
0xbf0ebf80,0x3f7b3ec4,0xbe483f35,0xbf55bf6d,0xbf558000,0xbe48bf6d,0x3f7b3f35,0xbf0e3ec4,0x3f0e3f80,0xbf7bbec4,0x3e48bf35,0x3f553f6d,
0x3f558000,0x3e483f6d,0xbf7bbf35,0x3f0ebec4,0x3f550000,0x3e483f6d,0xbf7bbf35,0x3f0ebec4,0xbf0ebf80,0x3f7b3ec4,0xbe483f35,0xbf55bf6d,
0xbf550000,0xbe48bf6d,0x3f7b3f35,0xbf0e3ec4,0x3f0e3f80,0xbf7bbec4,0x3e48bf35,0x3f553f6d,0x3f353f80,0xbf350000,0xbf35bf80,0x3f350000,
0x3f353f80,0xbf350000,0xbf35bf80,0x3f350000,0x3f353f80,0xbf350000,0xbf35bf80,0x3f350000,0x3f353f80,0xbf350000,0xbf35bf80,0x3f350000,
0x3f358000,0x3f353f80,0xbf358000,0xbf35bf80,0x3f358000,0x3f353f80,0xbf358000,0xbf35bf80,0x3f358000,0x3f353f80,0xbf358000,0xbf35bf80,
0x3f358000,0x3f353f80,0xbf358000,0xbf35bf80,0x3f0e0000,0x3f7b3f6d,0x3e483f35,0xbf55bec4,0x3f553f80,0xbe483ec4,0xbf7bbf35,0xbf0ebf6d,
0xbf0e0000,0xbf7bbf6d,0xbe48bf35,0x3f553ec4,0xbf55bf80,0x3e48bec4,0x3f7b3f35,0x3f0e3f6d,0xbf55bf80,0x3e48bec4,0x3f7b3f35,0x3f0e3f6d,
0x3f0e8000,0x3f7b3f6d,0x3e483f35,0xbf55bec4,0x3f553f80,0xbe483ec4,0xbf7bbf35,0xbf0ebf6d,0xbf0e8000,0xbf7bbf6d,0xbe48bf35,0x3f553ec4,
0x3f6d3f80,0x3ec43f35,0xbec40000,0xbf6dbf35,0xbf6dbf80,0xbec4bf35,0x3ec40000,0x3f6d3f35,0x3f6d3f80,0x3ec43f35,0xbec40000,0xbf6dbf35,
0xbf6dbf80,0xbec4bf35,0x3ec40000,0x3f6d3f35,0x3ec48000,0x3f6d3f35,0x3f6d3f80,0x3ec43f35,0xbec48000,0xbf6dbf35,0xbf6dbf80,0xbec4bf35,
0x3ec48000,0x3f6d3f35,0x3f6d3f80,0x3ec43f35,0xbec48000,0xbf6dbf35,0xbf6dbf80,0xbec4bf35,0x3e480000,0x3f0e3ec4,0x3f553f35,0x3f7b3f6d,
0xbf7bbf80,0xbf55bf6d,0xbf0ebf35,0xbe48bec4,0xbe480000,0xbf0ebec4,0xbf55bf35,0xbf7bbf6d,0x3f7b3f80,0x3f553f6d,0x3f0e3f35,0x3e483ec4,
0xbf7bbf80,0xbf55bf6d,0xbf0ebf35,0xbe48bec4,0xbe488000,0xbf0ebec4,0xbf55bf35,0xbf7bbf6d,0x3f7b3f80,0x3f553f6d,0x3f0e3f35,0x3e483ec4,
0x3e488000,0x3f0e3ec4,0x3f553f35,0x3f7b3f6d,0x3f803f80,0x80008000,0x3f803f80,0x80008000,0x3f803f80,0x80008000,0x3f803f80,0x80008000,
0x3f803f80,0x80008000,0x3f803f80,0x80008000,0x3f803f80,0x80008000,0x3f803f80,0x80008000,0x3f803f80,0xbbc98000,0x3f803f80,0xbd62bd49,
0x3f803f80,0xbc97bc49,0x3f7f3f80,0xbd8abd7b,0x3f803f80,0xbcfbbcc9,0x3f7f3f7f,0xbda3bd97,0x3f803f80,0xbd30bd17,0x3f7f3f7f,0xbdbcbdb0,
0x3f803f80,0xbc498000,0x3f7e3f7f,0xbde2bdc9,0x3f803f80,0xbd17bcc9,0x3f7e3f7e,0xbe0abdfb,0x3f803f80,0xbd7bbd49,0x3f7d3f7d,0xbe23be16,
0x3f7f3f7f,0xbdb0bd97,0x3f7c3f7c,0xbe3bbe2f,0x3f803f80,0xbc978000,0x3f7c3f7d,0xbe29be16,0x3f803f80,0xbd62bd17,0x3f7b3f7c,0xbe4ebe3b,
0x3f7f3f7f,0xbdbcbd97,0x3f793f7a,0xbe73be60,0x3f7e3f7e,0xbe04bde2,0x3f763f78,0xbe8cbe82,0x3f803f80,0xbcc98000,0x3f7a3f7b,0xbe60be48,
0x3f7f3f80,0xbd97bd49,0x3f773f78,0xbe89be79,0x3f7e3f7f,0xbdfbbdc9,0x3f733f75,0xbea1be95,0x3f7c3f7d,0xbe2fbe16,0x3f6f3f71,0xbeb8beac,
0x3f803f80,0xbcfb8000,0x3f763f78,0xbe8cbe79,0x3f7f3f80,0xbdbcbd7b,0x3f723f74,0xbeaabe9b,0x3f7d3f7e,0xbe1cbdfb,0x3f6c3f6f,0xbec7beb8,
0x3f7a3f7c,0xbe5abe3b,0x3f653f69,0xbee3bed5,0x3f803f80,0xbd178000,0x3f723f75,0xbea7be95,0x3f7e3f7f,0xbde2bd97,0x3f6b3f6f,0xbecabeb8,
0x3f7c3f7d,0xbe3bbe16,0x3f633f67,0xbeecbedb,0x3f783f7a,0xbe82be60,0x3f5a3f5f,0xbf06befc,0x3f803f80,0xbd308000,0x3f6d3f71,0xbec1beac,
0x3f7e3f7f,0xbe04bdb0,0x3f643f69,0xbee9bed5,0x3f7a3f7c,0xbe5abe2f,0x3f593f5f,0xbf08befc,0x3f753f78,0xbe98be82,0x3f4d3f53,0xbf1abf11,
0x3f803f80,0x80008000,0x3f803f80,0x80008000,0x3f803f80,0x80008000,0x3f803f80,0x80008000,0x3f803f80,0x80008000,0x3f803f80,0x80008000,
0x3f803f80,0x80008000,0x3f803f80,0x80008000,0x3f7f3f7f,0xbdd5bdc9,0x3f7d3f7d,0xbe1cbe16,0x3f7e3f7e,0xbdeebde2,0x3f7c3f7d,0xbe29be23,
0x3f7e3f7e,0xbe04bdfb,0x3f7c3f7c,0xbe35be2f,0x3f7d3f7e,0xbe10be0a,0x3f7b3f7c,0xbe42be3b,0x3f7a3f7b,0xbe54be48,0x3f743f75,0xbe9bbe95,
0x3f793f7a,0xbe6dbe60,0x3f723f73,0xbea7bea1,0x3f783f78,0xbe82be79,0x3f703f71,0xbeb2beac,0x3f763f77,0xbe8fbe89,0x3f6e3f6f,0xbebebeb8,
0x3f743f75,0xbe9ebe95,0x3f653f67,0xbee3bedb,0x3f713f72,0xbeafbea7,0x3f613f63,0xbef4beec,0x3f6d3f6f,0xbec1beb8,0x3f5c3f5f,0xbf02befc,
0x3f693f6b,0xbed2beca,0x3f573f5a,0xbf0abf06,0x3f6a3f6d,0xbecfbec4,0x3f513f55,0xbf13bf0e,0x3f653f67,0xbee6bedb,0x3f4a3f4e,0xbf1dbf18,
0x3f5f3f62,0xbefcbef1,0x3f423f46,0xbf27bf22,0x3f583f5c,0xbf09bf04,0x3f393f3e,0xbf31bf2c,0x3f5e3f62,0xbeffbef1,0x3f383f3e,0xbf32bf2c,
0x3f563f5a,0xbf0dbf06,0x3f2d3f33,0xbf3dbf37,0x3f4d3f51,0xbf1abf13,0x3f213f27,0xbf47bf42,0x3f433f48,0xbf26bf20,0x3f153f1b,0xbf50bf4c,
0x3f4f3f55,0xbf16bf0e,0x3f1b3f22,0xbf4cbf46,0x3f443f4a,0xbf25bf1d,0x3f0c3f13,0xbf57bf51,0x3f373f3e,0xbf33bf2c,0x3ef73f04,0xbf60bf5c,
0x3f2a3f31,0xbf40bf39,0x3ed53ee6,0xbf69bf65,0x3f3f3f46,0xbf2bbf22,0x3ef43f04,0xbf61bf5c,0x3f2f3f37,0xbf3abf33,0x3ecd3ee1,0xbf6bbf66,
0x3f1f3f27,0xbf49bf42,0x3ea43eb8,0xbf73bf6f,0x3f0d3f16,0xbf56bf4f,0x3e733e8f,0xbf79bf76,0x3f803f80,0xbd498000,0x3f673f6d,0xbedbbec4,
0x3f7d3f7f,0xbe16bdc9,0x3f5c3f62,0xbf04bef1,0x3f783f7b,0xbe79be48,0x3f4e3f55,0xbf18bf0e,0x3f713f75,0xbeacbe95,0x3f3e3f46,0xbf2cbf22,
0x3f803f80,0xbd628000,0x3f613f67,0xbef4bedb,0x3f7c3f7e,0xbe29bde2,0x3f523f5a,0xbf12bf06,0x3f763f7a,0xbe8cbe60,0x3f413f4a,0xbf28bf1d,
0x3f6d3f72,0xbec1bea7,0x3f2d3f37,0xbf3dbf33,0x3f803f80,0xbd7b8000,0x3f5a3f62,0xbf06bef1,0x3f7c3f7e,0xbe3bbdfb,0x3f483f51,0xbf20bf13,
0x3f743f78,0xbe9bbe79,0x3f333f3e,0xbf37bf2c,0x3f693f6f,0xbed5beb8,0x3f1b3f27,0xbf4cbf42,0x3f7f3f80,0xbd8a8000,0x3f523f5c,0xbf12bf04,
0x3f7b3f7e,0xbe4ebe0a,0x3f3d3f48,0xbf2dbf20,0x3f723f77,0xbeaabe89,0x3f243f31,0xbf45bf39,0x3f643f6b,0xbee9beca,0x3f083f16,0xbf59bf4f,
0x3f7f3f80,0xbd978000,0x3f4a3f55,0xbf1dbf0e,0x3f7a3f7d,0xbe60be16,0x3f313f3e,0xbf39bf2c,0x3f6f3f75,0xbeb8be95,0x3f133f22,0xbf51bf46,
0x3f5f3f67,0xbefcbedb,0x3ee63f04,0xbf65bf5c,0x3f7f3f80,0xbda38000,0x3f413f4e,0xbf28bf18,0x3f793f7d,0xbe73be23,0x3f243f33,0xbf45bf37,
0x3f6c3f73,0xbec7bea1,0x3f023f13,0xbf5cbf51,0x3f593f63,0xbf08beec,0x3ebb3ee1,0xbf6ebf66,0x3f7f3f80,0xbdb08000,0x3f373f46,0xbf33bf22,
0x3f783f7c,0xbe82be2f,0x3f163f27,0xbf4fbf42,0x3f693f71,0xbed5beac,0x3ee13f04,0xbf66bf5c,0x3f533f5f,0xbf11befc,0x3e8f3eb8,0xbf76bf6f,
0x3f7f3f80,0xbdbc8000,0x3f2d3f3e,0xbf3dbf2c,0x3f763f7c,0xbe8cbe3b,0x3f083f1b,0xbf59bf4c,0x3f653f6f,0xbee3beb8,0x3ebb3ee6,0xbf6ebf65,
0x3f4d3f5a,0xbf1abf06,0x3e423e8f,0xbf7bbf76,0x3f2c3f35,0xbf3ebf35,0x3eac3ec4,0xbf71bf6d,0x3f183f22,0xbf4ebf46,0x3e793e95,0xbf78bf75,
0x3f043f0e,0xbf5cbf55,0x3e163e48,0xbf7dbf7b,0x3edb3ef1,0xbf67bf62,0x3d493dc9,0xbf80bf7f,0x3f173f22,0xbf4fbf46,0x3e423e79,0xbf7bbf78,
0x3eff3f0c,0xbf5ebf57,0x3da33e0a,0xbf7fbf7e,0x3ecd3ee6,0xbf6bbf65,0xbcfb3cc9,0xbf80bf80,0x3e983eb2,0xbf75bf70,0xbe10bdb0,0xbf7dbf7f,
0x3f013f0e,0xbf5dbf55,0x3d173dc9,0xbf80bf7f,0x3eca3ee6,0xbf6bbf65,0xbdb0bcc9,0xbf7fbf80,0x3e8f3eac,0xbf76bf71,0xbe54be16,0xbf7abf7d,
0x3e233e60,0xbf7dbf7a,0xbea7be89,0xbf72bf77,0x3ed23ef1,0xbf69bf62,0xbdeebd49,0xbf7ebf80,0x3e923eb2,0xbf75bf70,0xbe7fbe3b,0xbf78bf7c,
0x3e1c3e60,0xbf7dbf7a,0xbec1bea1,0xbf6dbf73,0x3c973db0,0xbf80bf7f,0xbeffbee1,0xbf5ebf66,0x3ea13ec4,0xbf73bf6d,0xbe89be48,0xbf77bf7b,
0x3e2f3e79,0xbf7cbf78,0xbecfbeac,0xbf6abf71,0x3cc93dc9,0xbf80bf7f,0xbf09bef1,0xbf58bf62,0xbdfbbd49,0xbf7ebf80,0xbf27bf18,0xbf42bf4e,
0x3e5a3e95,0xbf7abf75,0xbed2beac,0xbf69bf71,0x3d623e0a,0xbf80bf7e,0xbf0dbef7,0xbf56bf60,0xbdd5bcc9,0xbf7fbf80,0xbf2dbf1d,0xbf3dbf4a,
0xbe86be3b,0xbf77bf7c,0xbf49bf3c,0xbf1fbf2e,0x3de23e48,0xbf7ebf7b,0xbf0cbef1,0xbf57bf62,0xbd7b3cc9,0xbf80bf80,0xbf2ebf1d,0xbf3cbf4a,
0xbe6dbe16,0xbf79bf7d,0xbf4cbf3e,0xbf1bbf2c,0xbecabea1,0xbf6bbf73,0xbf63bf58,0xbeecbf09,0x3bc93dc9,0xbf80bf7f,0xbf2bbf18,0xbf3fbf4e,
0xbe35bdb0,0xbf7cbf7f,0xbf4bbf3c,0xbf1cbf2e,0xbeb5be89,0xbf6fbf77,0xbf64bf58,0xbee9bf09,0xbf05bee1,0xbf5bbf66,0xbf75bf6e,0xbe92bebe,
0x3f7f3f80,0xbdc98000,0x3f223f35,0xbf46bf35,0x3f753f7b,0xbe95be48,0x3ef13f0e,0xbf62bf55,0x3f623f6d,0xbef1bec4,0x3e953ec4,0xbf75bf6d,
0x3f463f55,0xbf22bf0e,0x3dc93e48,0xbf7fbf7b,0x3f7f3f80,0xbdd58000,0x3f173f2c,0xbf4fbf3e,0x3f743f7a,0xbe9ebe54,0x3ed23f01,0xbf69bf5d,
0x3f5e3f6a,0xbeffbecf,0x3e5a3ea1,0xbf7abf73,0x3f3f3f4f,0xbf2bbf16,0x3bc93de2,0xbf80bf7e,0x3f7e3f80,0xbde28000,0x3f0c3f22,0xbf57bf46,
0x3f723f7a,0xbea7be60,0x3eb23ee6,0xbf70bf65,0x3f5a3f67,0xbf06bedb,0x3e0a3e79,0xbf7ebf78,0x3f373f4a,0xbf33bf1d,0xbdb03cc9,0xbf7fbf80,
0x3f7e3f80,0xbdee8000,0x3eff3f18,0xbf5ebf4e,0x3f713f79,0xbeafbe6d,0x3e923eca,0xbf75bf6b,0x3f563f65,0xbf0dbee6,0x3d623e2f,0xbf80bf7c,
0x3f2f3f44,0xbf3abf25,0xbe35bd7b,0xbf7cbf80,0x3f7e3f80,0xbdfb8000,0x3ee63f0e,0xbf65bf55,0x3f6f3f78,0xbeb8be79,0x3e603eac,0xbf7abf71,
0x3f513f62,0xbf13bef1,0xbcc93dc9,0xbf80bf7f,0x3f273f3e,0xbf42bf2c,0xbe89be16,0xbf77bf7d,0x3f7e3f80,0xbe048000,0x3ecd3f04,0xbf6bbf5c,
0x3f6d3f78,0xbec1be82,0x3e1c3e8f,0xbf7dbf76,0x3f4d3f5f,0xbf1abefc,0xbdd53cc9,0xbf7fbf80,0x3f1f3f37,0xbf49bf33,0xbeb5be6d,0xbf6fbf79,
0x3f7e3f80,0xbe0a8000,0x3eb23ef1,0xbf70bf62,0x3f6b3f77,0xbecabe89,0x3db03e60,0xbf7fbf7a,0x3f483f5c,0xbf20bf04,0xbe3bbd49,0xbf7cbf80,
0x3f163f31,0xbf4fbf39,0xbee1bea1,0xbf66bf73,0x3f7d3f80,0xbe108000,0x3e983edb,0xbf75bf67,0x3f693f76,0xbed2be8f,0x3c973e23,0xbf80bf7d,
0x3f433f58,0xbf26bf09,0xbe86bdfb,0xbf77bf7e,0x3f0d3f2a,0xbf56bf40,0xbf05beca,0xbf5bbf6b,0xbdc90000,0xbf7fbf80,0xbf46bf35,0xbf22bf35,
0xbe95be48,0xbf75bf7b,0xbf62bf55,0xbef1bf0e,0xbef1bec4,0xbf62bf6d,0xbf75bf6d,0xbe95bec4,0xbf22bf0e,0xbf46bf55,0xbf7fbf7b,0xbdc9be48,
0xbe4ebdc9,0xbf7bbf7f,0xbf5cbf4e,0xbf02bf18,0xbecdbe9b,0xbf6bbf74,0xbf73bf69,0xbea4bed5,0xbf15befc,0xbf50bf5f,0xbf7ebf7a,0xbdeebe60,
0xbf3dbf2a,0xbf2dbf40,0xbf7fbf80,0x3dbcbc49,0xbe9bbe48,0xbf74bf7b,0xbf6ebf62,0xbebebef1,0xbf01becf,0xbf5dbf6a,0xbf7dbf77,0xbe23be89,
0xbf2ebf18,0xbf3cbf4e,0xbf80bf80,0x3d7bbd49,0xbf53bf42,0xbf11bf27,0xbf76bf7c,0x3e8f3e2f,0xbecdbe95,0xbf6bbf75,0xbf79bf71,0xbe66beac,
0xbf1abf01,0xbf4dbf5d,0xbf80bf7e,0x3bc9bde2,0xbf45bf31,0xbf24bf39,0xbf79bf7e,0x3e733dfb,0xbf65bf57,0xbee3bf0c,0xbf64bf70,0x3ee93eb2,
0xbefcbec4,0xbf5fbf6d,0xbf7fbf7b,0xbd97be48,0xbf31bf18,0xbf39bf4e,0xbf7cbf80,0x3e2f3d49,0xbf58bf46,0xbf09bf22,0xbf6abf75,0x3ecf3e95,
0xbf73bf67,0xbea1bedb,0xbf4abf5c,0x3f1d3f04,0xbf15bef1,0xbf50bf62,0xbf7fbf80,0x3da3bd49,0xbf45bf2e,0xbf24bf3c,0xbf72bf7a,0x3eaa3e54,
0xbf68bf58,0xbed8bf09,0xbf54bf65,0x3f103ee6,0xbf7cbf74,0xbe35be9b,0xbf28bf40,0x3f413f2a,0xbf2abf0e,0xbf40bf55,0xbf79bf7f,0x3e6d3dc9,
0xbf57bf42,0xbf0cbf27,0xbf60bf6f,0x3ef73eb8,0xbf74bf67,0xbe9bbedb,0xbf37bf4e,0x3f333f18,0xbf80bf7c,0xbd17be2f,0xbf01bf1d,0x3f5d3f4a,
0xbf3dbf22,0xbf2dbf46,0xbf6dbf78,0x3ec13e79,0xbf65bf53,0xbee3bf11,0xbf49bf5d,0x3f1f3f01,0xbf7cbf73,0xbe35bea1,0xbf15bf31,0x3f503f39,
0xbf7fbf80,0x3dd5bd17,0xbeaabeec,0x3f723f63,0x3f7d3f80,0xbe168000,0x3e793ec4,0xbf78bf6d,0x3f673f75,0xbedbbe95,0xbd493dc9,0xbf80bf7f,
0x3f3e3f55,0xbf2cbf0e,0xbeacbe48,0xbf71bf7b,0x3f043f22,0xbf5cbf46,0xbf18bef1,0xbf4ebf62,0x3f7d3f80,0xbe1c8000,0x3e423eac,0xbf7bbf71,
0x3f653f74,0xbee3be9b,0xbdee3d17,0xbf7ebf80,0x3f383f51,0xbf32bf13,0xbed2be89,0xbf69bf77,0x3ef43f1b,0xbf61bf4c,0xbf2bbf0c,0xbf3fbf57,
0x3f7d3f80,0xbe238000,0x3e0a3e95,0xbf7ebf75,0x3f633f73,0xbeecbea1,0xbe3bbcc9,0xbf7cbf80,0x3f333f4e,0xbf37bf18,0xbef7beac,0xbf60bf71,
0x3ee13f13,0xbf66bf51,0xbf3cbf1d,0xbf2ebf4a,0x3f7c3f80,0xbe298000,0x3da33e79,0xbf7fbf78,0x3f613f72,0xbef4bea7,0xbe7fbdb0,0xbf78bf7f,
0x3f2d3f4a,0xbf3dbf1d,0xbf0dbecf,0xbf56bf6a,0x3ecd3f0c,0xbf6bbf57,0xbf4bbf2e,0xbf1cbf3c,0x3f7c3f80,0xbe2f8000,0x3cc93e48,0xbf80bf7b,
0x3f5f3f71,0xbefcbeac,0xbea1be16,0xbf73bf7d,0x3f273f46,0xbf42bf22,0xbf1dbef1,0xbf4abf62,0x3eb83f04,0xbf6fbf5c,0xbf58bf3e,0xbf09bf2c,
0x3f7c3f80,0xbe358000,0xbcfb3e16,0xbf80bf7d,0x3f5c3f70,0xbf02beb2,0xbec1be54,0xbf6dbf7a,0x3f213f42,0xbf47bf27,0xbf2dbf09,0xbf3dbf58,
0x3ea43ef7,0xbf73bf60,0xbf64bf4c,0xbee9bf1b,0x3f7c3f80,0xbe3b8000,0xbdb03dc9,0xbf7fbf7f,0x3f5a3f6f,0xbf06beb8,0xbee1be89,0xbf66bf77,
0x3f1b3f3e,0xbf4cbf2c,0xbf3cbf18,0xbf2ebf4e,0x3e8f3ee6,0xbf76bf65,0xbf6ebf58,0xbebebf09,0x3f7b3f80,0xbe428000,0xbe103d49,0xbf7dbf80,
0x3f573f6e,0xbf0abebe,0xbeffbea7,0xbf5ebf72,0x3f153f39,0xbf50bf31,0xbf49bf27,0xbf1fbf42,0x3e733ed5,0xbf79bf69,0xbf75bf63,0xbe92beec,
0xbf4ebf35,0xbf18bf35,0xbf5cbf6d,0x3f043ec4,0xbf71bf62,0xbeacbef1,0xbf2cbf46,0x3f3e3f22,0xbf80bf7b,0xbd49be48,0xbedbbf0e,0x3f673f55,
0xbf78bf7f,0x3e793dc9,0xbe16be95,0x3f7d3f75,0xbf5cbf46,0xbf02bf22,0xbf45bf5c,0x3f243f04,0xbf79bf6e,0xbe66bebe,0xbf0abf2a,0x3f573f40,
0xbf7fbf7f,0x3da3bd97,0xbe86becf,0x3f773f6a,0xbf6dbf79,0x3ec13e6d,0x3d30bde2,0x3f803f7e,0xbf69bf55,0xbed5bf0e,0xbf2abf46,0x3f403f22,
0xbf7ebf77,0xbde2be89,0xbecabf09,0x3f6b3f58,0xbf7abf80,0x3e543d49,0xbdb0be79,0x3f7f3f78,0xbf5dbf6f,0x3f013eb8,0x3e6d3d97,0x3f793f7f,
0xbf73bf62,0xbea4bef1,0xbf0abf2c,0x3f573f3e,0xbf80bf7d,0x3bc9be23,0xbe73beca,0x3f793f6b,0xbf72bf7c,0x3eaa3e2f,0x3dbcbd97,0x3f7f3f7f,
0xbf49bf60,0x3f1f3ef7,0x3ed23e82,0x3f693f78,0xbf7abf6d,0xbe60bec4,0xbecfbf0e,0x3f6a3f55,0xbf7ebf80,0x3dfbbd49,0xbd97be79,0x3f7f3f78,
0xbf65bf75,0x3ee63e95,0x3e893dc9,0x3f773f7f,0xbf31bf4e,0x3f393f18,0x3f133edb,0x3f513f67,0xbf7ebf75,0xbdeebe95,0xbe86bedb,0x3f773f67,
0xbf79bf80,0x3e733d7b,0x3dbcbdb0,0x3f7f3f7f,0xbf54bf6a,0x3f103ecf,0x3ede3e89,0x3f673f77,0xbf15bf37,0x3f503f33,0x3f383f16,0x3f323f4f,
0xbf80bf7b,0xbc49be48,0xbde2be95,0x3f7e3f75,0xbf70bf7c,0x3eb23e2f,0x3e823d97,0x3f783f7f,0xbf40bf5c,0x3f2a3f04,0x3f163edb,0x3f4f3f67,
0xbeecbf1d,0x3f633f4a,0x3f573f39,0x3f0c3f31,0xbf7fbf7f,0x3dbcbdc9,0x3d30be16,0x3f803f7d,0xbf64bf76,0x3ee93e8f,0x3ed23e6d,0x3f693f79,
0xbf28bf4a,0x3f413f1d,0x3f383f13,0x3f323f51,0xbeaabf01,0x3f723f5d,0x3f6d3f57,0x3ec13f0c,
};
__device__ const __align__(128) uint64_t c_inv[16384] = {
0x3f003f003f003f00,0x3f003f003f003f00,0x3f003f003f003f00,0x3f003f003f003f00,0x3f003f003f003f00,0x3f003f003f003f00,0x3f003f003f003f00,0x3f003f003f003f00,
0xbf00bf003f003f00,0xbf00bf003f003f00,0xbf00bf003f003f00,0xbf00bf003f003f00,0xbf00bf003f003f00,0xbf00bf003f003f00,0xbf00bf003f003f00,0xbf00bf003f003f00,
0x3f733f7a3f753f7b,0x3f6f3f773f713f78,0x3f7e3f803f7f3f80,0x3f7c3f7f3f7d3f80,0x3f423f513f463f55,0x3f393f4a3f3e3f4e,0x3f5f3f6a3f623f6d,0x3f583f653f5c3f67,
0xbea1be60be95be48,0xbeb8be89beacbe79,0xbdfbbcc9bdc98000,0xbe2fbd97be16bd49,0xbf27bf13bf22bf0e,0xbf31bf1dbf2cbf18,0xbefcbecfbef1bec4,0xbf09bee6bf04bedb,
0x3f043f2c3f0e3f35,0x3edb3f183ef13f22,0x3e163eac3e483ec4,0x3d493e793dc93e95,0x3f783f803f7b3f80,0x3f713f7d3f753f7f,0x3f4e3f673f553f6d,0x3f3e3f5c3f463f62,
0xbf5cbf3ebf55bf35,0xbf67bf4ebf62bf46,0xbf7dbf71bf7bbf6d,0xbf80bf78bf7fbf75,0xbe79bd49be488000,0xbeacbe16be95bdc9,0xbf18bedbbf0ebec4,0xbf2cbf04bf22bef1,
0xbf09be89bef1be48,0xbf27becfbf18beac,0x3cc93ea13dc93ec4,0xbdfb3e2fbd493e79,0x3f133f4a3f223f55,0x3ee63f313f043f3e,0x3f6f3f7f3f753f80,0x3f5f3f7a3f673f7d,
0xbf58bf77bf62bf7b,0xbf42bf6abf4ebf71,0xbf80bf73bf7fbf6d,0xbf7ebf7cbf80bf78,0xbf51bf1dbf46bf0e,0xbf65bf39bf5cbf2c,0xbeb8bd97be958000,0xbefcbe60bedbbe16,
0x3f623f7f3f6d3f80,0x3f463f753f553f7b,0x3e953f223ec43f35,0x3dc93ef13e483f0e,0xbef1bdc9bec40000,0xbf22be95bf0ebe48,0xbf75bf46bf6dbf35,0xbf7fbf62bf7bbf55,
0xbef1bdc9bec48000,0xbf22be95bf0ebe48,0xbf75bf46bf6dbf35,0xbf7fbf62bf7bbf55,0xbf62bf7fbf6dbf80,0xbf46bf75bf55bf7b,0xbe95bf22bec4bf35,0xbdc9bef1be48bf0e,
0xbcc93ee63dc93f0e,0xbe893e60be163eac,0x3f513f7e3f623f80,0x3f273f6f3f3e3f78,0xbf6abf7fbf75bf7b,0xbf4abf7cbf5cbf80,0xbf58befcbf46bec4,0xbf73bf31bf67bf18,
0xbf80bf65bf7fbf55,0xbf77bf7abf7dbf71,0xbf13bdfbbef18000,0xbf42beb8bf2cbe79,0x3ecfbd973e95be48,0x3f1d3e2f3f043d49,0xbf09bf5fbf22bf6d,0xbea1bf39bedbbf4e,
0xbf80bf4ebf7bbf35,0xbf78bf71bf7fbf62,0xbedbbf5cbf0ebf6d,0xbe16bf2cbe95bf46,0x3f3e3f7d3f553f80,0x3f043f673f223f75,0xbeac3e79be483ec4,0xbf18bd49bef13dc9,
0xbd49bf18be48bf35,0x3e79beac3dc9bef1,0x3f673f043f553ec4,0x3f7d3f3e3f753f22,0xbf2cbe16bf0e8000,0xbf5cbedbbf46be95,0xbf71bf78bf7bbf6d,0xbf4ebf80bf62bf7f,
0x3e89becf3dc9bf0e,0x3f13bd973edbbe79,0xbf65bf7abf75bf6d,0xbf31bf7ebf4ebf80,0xbf1d3cc9bef13e48,0xbf58bea1bf3ebe16,0x3f273f7c3f463f80,0x3eb83f5f3f043f71,
0x3f773f6a3f7f3f55,0x3f513f7f3f673f78,0x3ee6be603e95bec4,0x3f393dfb3f18bd49,0xbf4abf80bf62bf7b,0xbf09bf73bf2cbf7d,0xbf42be2fbf228000,0xbf6fbefcbf5cbeac,
0x3f0e3f7b3f353f80,0x3e483f553ec43f6d,0xbf55be48bf350000,0xbf7bbf0ebf6dbec4,0xbf0ebf7bbf35bf80,0xbe48bf55bec4bf6d,0x3f553e483f350000,0x3f7b3f0e3f6d3ec4,
0xbf55be48bf358000,0xbf7bbf0ebf6dbec4,0xbf0ebf7bbf35bf80,0xbe48bf55bec4bf6d,0x3f553e483f358000,0x3f7b3f0e3f6d3ec4,0x3f0e3f7b3f353f80,0x3e483f553ec43f6d,
0xbf77becfbf62be48,0xbf7cbf42bf80bf18,0x3ee63f7a3f223f80,0x3cc93f4a3e793f67,0x3f7e3f393f7f3f0e,0x3f583f733f713f5c,0xbd97bf51be95bf6d,0x3eb8befc3e16bf2c,
0xbe89bf6abef1bf7b,0x3e2fbf27bd49bf4e,0xbf65be60bf468000,0xbf80bf1dbf78bedb,0xbdfb3f313dc93f55,0xbf093ea1beac3f04,0x3f7f3f133f753ec4,0x3f6f3f5f3f7d3f3e,
0x3edbbf043e48bf35,0x3f4ebd493f22be95,0x3f2c3f7d3f553f6d,0x3e793f713ef13f7f,0x3eac3f783f0e3f80,0xbe163f3e3dc93f62,0xbf80bf18bf7bbec4,0xbf5cbf67bf75bf46,
0x3f673f5c3f7b3f35,0x3f183f803f463f75,0xbf3e3e16bf0e3ec4,0xbf78beacbf62bdc9,0xbf71be79bf558000,0xbf7dbf2cbf7fbef1,0x3d49bf4ebe48bf6d,0x3f04bedb3e95bf22,
0x3cc93f653e953f7b,0xbefc3f09be793f3e,0x3f51bdfb3f22bec4,0x3f7f3ecf3f713e16,0xbf6fbf42bf7fbf0e,0xbf1dbf7cbf4ebf67,0x3e603f773ef13f80,0xbea13f31bd493f5c,
0xbf80bee6bf75be48,0xbf5fbf58bf78bf2c,0x3f133f7e3f463f6d,0x3d973f6a3eac3f7d,0x3eb8bf273dc9bf55,0x3f4abe2f3f18bedb,0xbf7abe89bf628000,0xbf73bf39bf80bf04,
0x3dc93f753ec43f80,0xbef13f22be483f55,0xbf46bf62bf6dbf35,0xbe95bf7fbf0ebf7b,0x3f7f3e953f6d0000,0x3f623f463f7b3f0e,0xbf223ef1bec43f35,0xbf75bdc9bf553e48,
0xbf7fbe95bf6d8000,0xbf62bf46bf7bbf0e,0x3f22bef13ec4bf35,0x3f753dc93f55be48,0x3dc93f753ec43f80,0xbef13f22be483f55,0xbf46bf62bf6dbf35,0xbe95bf7fbf0ebf7b,
0xbf09bf77bf46bf55,0x3d97bf6fbe79bf80,0xbcc93f733e953f80,0xbf1d3f13beac3f4e,0xbf7cbdfbbf623e48,0xbf65bf31bf7dbedb,0x3f6a3f273f7f3ec4,0x3efc3f7a3f3e3f5c,
0x3f58be893f22bf0e,0x3f7f3eb83f783d49,0xbf80bea1bf758000,0xbf4abf51bf71bf18,0xbe2fbf7ebef1bf7b,0x3ee6bf393e16bf67,0xbecf3f42bdc93f6d,0xbf5f3e60bf2c3f04,
0x3f183f673f553f35,0xbd493f783e953f7f,0xbf5cbf2cbf7bbec4,0xbeacbf7dbf22bf62,0xbe163f713e483f80,0xbf3e3f04bef13f46,0xbe79bf80bf0ebf6d,0x3edbbf4e3dc9bf75,
0xbf4e3edbbf0e3f35,0xbf80be79bf753dc9,0x3f04bf3e3e48bf6d,0x3f71be163f46bef1,0xbf7dbeacbf7b8000,0xbf2cbf5cbf62bf22,0x3f78bd493f55bec4,0x3f673f183f7f3e95,
0xbea1bf7abf22bf55,0x3ecfbf5f3d49bf7d,0x3dfb3f803ef13f6d,0xbf133f42be793f71,0x3d97bf7cbe95bf7b,0x3f39bf1d3edbbf5c,0xbe893f6f3dc93f80,0xbf583ee6bf183f3e,
0x3f73be603f46bf0e,0x3f6a3efc3f803e16,0xbf7e3cc9bf623ec4,0xbf51bf27bf78beac,0x3f7f3e2f3f75be48,0x3f313f4a3f673f04,0xbf77beb8bf7f8000,0xbf09bf65bf4ebf2c,
0xbec43f6d00003f80,0xbf6d3ec4bf353f35,0x3ec4bf6d0000bf80,0x3f6dbec43f35bf35,0xbec43f6d00003f80,0xbf6d3ec4bf353f35,0x3ec4bf6d0000bf80,0x3f6dbec43f35bf35,
0xbf6dbec4bf808000,0xbec4bf6dbf35bf35,0x3f6d3ec43f808000,0x3ec43f6d3f353f35,0xbf6dbec4bf808000,0xbec4bf6dbf35bf35,0x3f6d3ec43f808000,0x3ec43f6d3f353f35,
0x3f27bf513e95bf7b,0x3f80bdfb3f67bf04,0xbefc3f6abdc93f80,0xbf7a3ea1bf4e3f2c,0x3f65bf093f22bf55,0x3f6f3e893f80be16,0xbf4a3f31bef13f6d,0xbf7cbd97bf783eac,
0x3f423f133f753e48,0x3cc93f7e3edb3f5c,0xbf5fbecfbf7f8000,0xbe60bf73bf18bf3e,0x3ee63f583f463f0e,0xbeb83f773d493f7d,0xbf1dbf39bf62bec4,0x3e2fbf7fbe79bf71,
0xbf7d3eacbf553f35,0xbf3ebf04bf75bdc9,0x3f783d493f7bbec4,0x3edb3f4e3f463ef1,0xbf183f67be483f80,0xbf803e79bf623f22,0x3f5cbf2c3f0ebf6d,0x3f713e163f7fbe95,
0xbe16bf71bf0ebf35,0x3f2cbf5c3e95bf7f,0xbe793f803e483f6d,0xbf673f18bf223f62,0xbf4ebedbbf7b8000,0xbd49bf78bef1bf46,0x3f043f3e3f553ec4,0xbeac3f7d3dc93f75,
0x3f133f1d3f623e48,0xbea13f803e163f67,0xbf6fbd97bf7f3ec4,0xbe89bf58bf2cbf04,0x3f7abefc3f46bf55,0x3f423ecf3f78bd49,0xbf313f65be953f80,0xbf7e3e2fbf713f18,
0xbf513f4abef13f7b,0xbf73bcc9bf7d3edb,0x3eb8bf7fbdc9bf6d,0x3f77bf093f3ebf5c,0x3e603f5f3f223f0e,0xbf273f6abe793f80,0xbf39bee6bf758000,0x3dfbbf7cbeacbf4e,
0xbf463f62bec43f80,0xbf753dc9bf7b3f0e,0x3f7fbe953f6dbf35,0x3ef13f223f553e48,0xbf22bef1bf6d0000,0x3e95bf7fbe48bf55,0xbdc93f753ec43f35,0xbf623f46bf0e3f7b,
0xbf22bef1bf6d8000,0x3e95bf7fbe48bf55,0xbdc93f753ec43f35,0xbf623f46bf0e3f7b,0x3f46bf623ec4bf80,0x3f75bdc93f7bbf0e,0xbf7f3e95bf6d3f35,0xbef1bf22bf55be48,
0x3f6abd973f7fbf0e,0x3dfb3f513f183edb,0xbf583f5fbef13f80,0xbf653cc9bf803f04,0xbf393f73be953f7b,0xbf773e60bf783f2c,0xbe2fbf4abf22bec4,0x3f42bf6f3eacbf7d,
0xbecf3f7f3dc93f55,0xbf7e3f13bf4e3f67,0xbf09befcbf628000,0x3ee6bf80bd49bf5c,0xbf31bea1bf753e48,0x3e89bf7abe79bf3e,0x3f7cbf1d3f46bf6d,0x3f273eb83f71be16,
0x3eacbf78be48bf35,0x3f7dbf2c3f46bf75,0xbf803f18bf553f6d,0xbf04bedbbf623dc9,0xbf673f5cbf0e3f80,0xbf4ebd49bf7f3ef1,0x3f3e3e163f7bbec4,0xbe793f713e953f22,
0x3f71be793f7bbf35,0x3e163f3e3f223e95,0xbd49bf4ebf0ebec4,0x3f5cbf673ef1bf7f,0xbedbbf04bf558000,0x3f18bf803dc9bf62,0xbf2c3f7dbe483f6d,0xbf783eacbf753f46,
0xbf4a3cc9bf7f3f0e,0x3e60bf65beacbf04,0x3f42bf7c3e95bf6d,0x3f6abe893f7dbf3e,0x3efc3eb83f62be48,0xbf133f7fbd493f4e,0xbf733f58bf223f80,0xbf31bdfbbf783edb,
0x3f1dbf803dc9bf55,0x3f7abee63f71bf5c,0x3f273e2f3f75bec4,0xbecf3f773e163f2c,0xbf5f3f6fbef13f7b,0xbf513d97bf803f18,0xbea1bf09bf468000,0x3f39bf7e3e79bf67,
0xbf7b3f55bf353f80,0xbf0ebe48bf6d3ec4,0x3e483f0e3f350000,0xbf553f7bbec43f6d,0x3f7bbf553f35bf80,0x3f0e3e483f6dbec4,0xbe48bf0ebf350000,0x3f55bf7b3ec4bf6d,
0xbe48bf0ebf358000,0x3f55bf7b3ec4bf6d,0xbf7b3f55bf353f80,0xbf0ebe48bf6d3ec4,0x3e483f0e3f358000,0xbf553f7bbec43f6d,0x3f7bbf553f35bf80,0x3f0e3e483f6dbec4,
0xbdfb3f393ef13e48,0xbf7a3f65bf2c3f7d,0xbf7f3f51bf463f80,0xbecfbe89bf5c3eac,0x3efcbf6fbdc9bf0e,0x3f7cbf273f67bf78,0x3f73bf093f75bf6d,0x3cc93f1d3f183d49,
0xbf7e3f31bf623f7b,0xbe60bee6bf3e3e16,0xbd97bf13bf228000,0x3f6abf773f04bf71,0x3f5fbeb83f7fbf55,0xbe2f3f423edb3e79,0xbea13f583e953ec4,0xbf803f4abf4e3f80,
0x3f2cbe163f7bbf35,0xbf043f673dc93ef1,0x3f71bf783f0ebf6d,0x3f18bd493f75bf22,0xbf803f4ebf553f80,0xbe79beacbf463e95,0xbedb3f5c3e483ec4,0xbf7d3f3ebf623f7f,
0xbf3e3f7dbe483f35,0xbf5c3edbbf7f3f62,0x3eac3e793f55bec4,0xbf4e3f80be953f46,0x3d49bf18bf0e8000,0x3f78bf713f22bf75,0xbf673f04bf7b3f6d,0x3e16bf2cbef1bdc9,
0x3f6fbf273f75bf7b,0xbdfb3f133f04bd49,0x3e603e893f46bec4,0xbf653f80bedb3f4e,0xbf313f73bdc93f0e,0xbf5f3f09bf7d3f71,0xbf7c3f4abf623f80,0xbd97becfbf2c3e79,
0xbeb83f423e953e48,0xbf7e3f51bf5c3f80,0xbf7a3f77bf223f6d,0xbee6bcc9bf673f18,0xbf393ea1bf7f3f55,0x3efcbf58be16beac,0x3e2fbf1dbef18000,0x3f7fbf6a3f3ebf78,
0xbf753f46bf6d3f80,0x3dc9bef1bf0e3e48,0xbf623f7fbec43f35,0xbf223e95bf7b3f55,0xbe953f223ec40000,0xbf7f3f62bf553f7b,0x3ef1bdc93f6dbf35,0xbf463f75be483f0e,
0x3e95bf22bec48000,0x3f7fbf623f55bf7b,0xbef13dc9bf6d3f35,0x3f46bf753e48bf0e,0xbf753f46bf6d3f80,0x3dc9bef1bf0e3e48,0xbf623f7fbec43f35,0xbf223e95bf7b3f55,
0xbf7c3f7ebf223f55,0xbea13cc9bf5c3f2c,0xbf6a3f42bf753f80,0x3e89bf09bedb3e16,0xbe603efc3ef1be48,0xbf7f3f6fbf4e3f71,0xbf393f65bdc93ec4,0xbf4a3f13bf803f78,
0xbe2fbdfbbf463f0e,0x3f73bf803f04bf3e,0x3ecfbf27be958000,0x3f77bf583f67bf7d,0xbf7a3f5fbf623f7b,0x3d97beb8bf183eac,0xbf313ee6bf7f3f6d,0x3f1dbf51bd49be79,
0xbf783f80bf0e3f35,0xbeac3e16bf623f46,0xbf4e3f67be483ec4,0xbf2c3f04bf7f3f75,0xbf5c3f3ebf7b3f80,0x3edbbf18be953dc9,0xbf7d3f71bf553f6d,0x3d49be79bf223ef1,
0xbe793d49bf553f35,0x3f71bf7d3ef1bf22,0xbf183edbbf7b3f6d,0x3f3ebf5c3dc9be95,0x3f04bf2cbe488000,0x3f67bf4e3f75bf7f,0x3e16beacbf0e3ec4,0x3f80bf783f46bf62,
0xbf7f3f7cbf463f55,0x3cc9bdfbbf2c3f18,0xbf773f6fbf623f6d,0x3e60bea1bf043edb,0xbf653f58bf753f7b,0x3ecfbefcbeac3e79,0xbf4a3f39bf7f3f80,0x3f13bf27be163d49,
0x3d97be2fbf223f0e,0x3f80bf7e3f3ebf4e,0x3e89beb8bef13ec4,0x3f7abf733f5cbf67,0x3ee6bf09be953e48,0x3f6abf5f3f71bf78,0x3f1dbf31bdc98000,0x3f51bf423f7dbf80,
0x3f003f003f003f00,0x3f003f003f003f00,0x3f003f003f003f00,0x3f003f003f003f00,0x3f003f003f003f00,0x3f003f003f003f00,0x3f003f003f003f00,0x3f003f003f003f00,
0xbf00bf003f003f00,0xbf00bf003f003f00,0xbf00bf003f003f00,0xbf00bf003f003f00,0xbf00bf003f003f00,0xbf00bf003f003f00,0xbf00bf003f003f00,0xbf00bf003f003f00,
0x3ee63f093ef13f0e,0x3ecf3efc3edb3f04,0x3f1d3f313f223f35,0x3f133f273f183f2c,0x3d973e2f3dc93e48,0x3cc93dfb3d493e16,0x3e893eb83e953ec4,0x3e603ea13e793eac,
0xbf65bf58bf62bf55,0xbf6abf5fbf67bf5c,0xbf4abf39bf46bf35,0xbf51bf42bf4ebf3e,0xbf7fbf7cbf7fbf7b,0xbf80bf7ebf80bf7d,0xbf77bf6fbf75bf6d,0xbf7abf73bf78bf71,
0xbf5cbf3ebf55bf35,0xbf67bf4ebf62bf46,0xbf7dbf71bf7bbf6d,0xbf80bf78bf7fbf75,0xbe79bd49be480000,0xbeacbe16be95bdc9,0xbf18bedbbf0ebec4,0xbf2cbf04bf22bef1,
0xbf04bf2cbf0ebf35,0xbedbbf18bef1bf22,0xbe16beacbe48bec4,0xbd49be79bdc9be95,0xbf78bf80bf7bbf80,0xbf71bf7dbf75bf7f,0xbf4ebf67bf55bf6d,0xbf3ebf5cbf46bf62,
0xbe60befcbe95bf0e,0xbd97beb8be16bedb,0xbf39bf65bf46bf6d,0xbf1dbf51bf2cbf5c,0xbf7cbf7ebf7fbf7b,0xbf73bf80bf78bf80,0xbf6abf42bf62bf35,0xbf77bf58bf71bf4e,
0x3f7a3f5f3f753f55,0x3f7f3f6f3f7d3f67,0x3f313ee63f223ec4,0x3f4a3f133f3e3f04,0x3e2fbdfb3dc9be48,0x3ea13cc93e79bd49,0xbecfbf27bef1bf35,0xbe89bf09beacbf18,
0xbf62bf7fbf6dbf80,0xbf46bf75bf55bf7b,0xbe95bf22bec4bf35,0xbdc9bef1be48bf0e,0x3ef13dc93ec40000,0x3f223e953f0e3e48,0x3f753f463f6d3f35,0x3f7f3f623f7b3f55,
0x3ef13dc93ec48000,0x3f223e953f0e3e48,0x3f753f463f6d3f35,0x3f7f3f623f7b3f55,0x3f623f7f3f6d3f80,0x3f463f753f553f7b,0x3e953f223ec43f35,0x3dc93ef13e483f0e,
0x3f393ea13f223e48,0x3f5f3f093f4e3edb,0xbe2fbf1dbe95bf35,0x3d97becfbd49bf04,0x3eb83f423ef13f55,0x3dfb3f133e793f2c,0x3f7a3f773f7f3f6d,0x3f653f803f713f7d,
0x3f313f733f463f7b,0x3efc3f583f183f67,0x3f7c3f4a3f753f35,0x3f7f3f6a3f803f5c,0xbf6fbf27bf62bf0e,0xbf7ebf51bf78bf3e,0xbe603e89bdc93ec4,0xbee63cc9beac3e16,
0x3d493f183e483f35,0xbe793eacbdc93ef1,0xbf67bf04bf55bec4,0xbf7dbf3ebf75bf22,0x3f2c3e163f0e0000,0x3f5c3edb3f463e95,0x3f713f783f7b3f6d,0x3f4e3f803f623f7f,
0xbf80bf4ebf7bbf35,0xbf78bf71bf7fbf62,0xbedbbf5cbf0ebf6d,0xbe16bf2cbe95bf46,0x3f3e3f7d3f553f80,0x3f043f673f223f75,0xbeac3e79be483ec4,0xbf18bd49bef13dc9,
0xbefcbf6fbf22bf7b,0xbe2fbf42beacbf5c,0xbf73bf09bf62bec4,0xbf80bf4abf7dbf2c,0x3dfb3f393e953f55,0xbe603ee6bd493f18,0x3f7f3f513f7f3f35,0x3f6a3f773f783f67,
0x3f5f3eb83f463e48,0x3f7c3f273f713f04,0xbea1bf58bef1bf6d,0x3cc9bf1dbe16bf3e,0xbf7ebf31bf75bf0e,0xbf7abf65bf80bf4e,0xbd973f133dc93f35,0xbecf3e89be793edb,
0x3f0e3f7b3f353f80,0x3e483f553ec43f6d,0xbf55be48bf350000,0xbf7bbf0ebf6dbec4,0xbf0ebf7bbf35bf80,0xbe48bf55bec4bf6d,0x3f553e483f350000,0x3f7b3f0e3f6d3ec4,
0xbf55be48bf358000,0xbf7bbf0ebf6dbec4,0xbf0ebf7bbf35bf80,0xbe48bf55bec4bf6d,0x3f553e483f358000,0x3f7b3f0e3f6d3ec4,0x3f0e3f7b3f353f80,0x3e483f553ec43f6d,
0xbf5fbf6fbf75bf55,0xbf13bf7fbf3ebf7d,0xbea13f09bdc93f35,0xbf313dfbbf043eac,0x3f1d3f803f463f7b,0x3e603f653edb3f78,0x3f27be2f3ef1bec4,0x3f6a3e893f4e3d49,
0x3efcbeb83e95bf0e,0x3f513d973f2cbe16,0xbf73bf58bf7fbf35,0xbf39bf7ebf5cbf71,0xbf4abcc9bf223e48,0xbf7abee6bf67be79,0x3f423f7c3f623f6d,0x3ecf3f773f183f80,
0x3f673f5c3f7b3f35,0x3f183f803f463f75,0xbf3e3e16bf0e3ec4,0xbf78beacbf62bdc9,0xbf71be79bf550000,0xbf7dbf2cbf7fbef1,0x3d49bf4ebe48bf6d,0x3f04bedb3e95bf22,
0xbedb3f04be483f35,0xbf4e3d49bf223e95,0xbf2cbf7dbf55bf6d,0xbe79bf71bef1bf7f,0xbeacbf78bf0ebf80,0x3e16bf3ebdc9bf62,0x3f803f183f7b3ec4,0x3f5c3f673f753f46,
0xbf39bf73bf62bf55,0xbe89bf7abf04bf80,0xbe2f3f4a3dc93f6d,0xbf273eb8bedb3f18,0x3f6a3d973f46be48,0x3f7e3f133f7d3eac,0xbf58bf5fbf75bf35,0xbee6bf80bf2cbf78,
0x3f31bea13ef1bf0e,0x3f773e603f5cbd49,0xbf7cbf1dbf7fbec4,0xbf42bf6fbf67bf4e,0x3ecf3f7f3f223f7b,0xbdfb3f513e163f71,0x3f09befc3e95bf35,0x3f653cc93f3ebe79,
0xbdc9bf75bec4bf80,0x3ef1bf223e48bf55,0x3f463f623f6d3f35,0x3e953f7f3f0e3f7b,0xbf7fbe95bf6d0000,0xbf62bf46bf7bbf0e,0x3f22bef13ec4bf35,0x3f753dc93f55be48,
0x3f7f3e953f6d8000,0x3f623f463f7b3f0e,0xbf223ef1bec43f35,0xbf75bdc9bf553e48,0xbdc9bf75bec4bf80,0x3ef1bf223e48bf55,0x3f463f623f6d3f35,0x3e953f7f3f0e3f7b,
0xbe603f5f3dc93f7b,0xbf423ecfbf043f2c,0x3f39bee63ef1bf35,0x3f7e3e2f3f67be16,0x3f513f4a3f753f0e,0x3ea13f803f183f71,0xbeb8bf7fbf22bf6d,0x3e89bf58bd49bf78,
0xbf7abefcbf7fbe48,0xbf27bf6abf5cbf3e,0x3f313f653f623f35,0x3dfb3f7c3edb3f7d,0xbf133f1dbe953f55,0xbf733cc9bf4e3eac,0x3f6fbd973f46bec4,0x3f773f093f803e79,
0x3f4ebedb3f0ebf35,0x3f803e793f75bdc9,0xbf043f3ebe483f6d,0xbf713e16bf463ef1,0x3f7d3eac3f7b0000,0x3f2c3f5c3f623f22,0xbf783d49bf553ec4,0xbf67bf18bf7fbe95,
0x3f183f673f553f35,0xbd493f783e953f7f,0xbf5cbf2cbf7bbec4,0xbeacbf7dbf22bf62,0xbe163f713e483f80,0xbf3e3f04bef13f46,0xbe79bf80bf0ebf6d,0x3edbbf4e3dc9bf75,
0xbf65bf09bf7fbe48,0xbeb8bf77bf2cbf4e,0x3f4a3f313f753ec4,0x3e2f3f7f3f043f67,0xbf27bf51bf62bf0e,0x3cc9bf7ebeacbf78,0x3efc3f6a3f463f35,0xbe603f733e163f80,
0x3ee6bf583dc9bf7b,0x3f6fbe893f3ebf18,0xbf1d3f39be953f6d,0xbf7c3d97bf5c3edb,0x3f42bf133ef1bf55,0x3f803dfb3f71be79,0xbf5f3ecfbf223f35,0xbf7abea1bf7d3d49,
0xbec43f6d00003f80,0xbf6d3ec4bf353f35,0x3ec4bf6d0000bf80,0x3f6dbec43f35bf35,0xbec43f6d00003f80,0xbf6d3ec4bf353f35,0x3ec4bf6d0000bf80,0x3f6dbec43f35bf35,
0xbf6dbec4bf808000,0xbec4bf6dbf35bf35,0x3f6d3ec43f808000,0x3ec43f6d3f353f35,0xbf6dbec4bf808000,0xbec4bf6dbf35bf35,0x3f6d3ec43f808000,0x3ec43f6d3f353f35,
0x3f7fbe2f3f62bf0e,0x3f393f1d3f713e79,0xbf773eb8bf463f35,0xbf58bee6bf7dbd49,0x3f733e603f7fbe48,0x3ecf3f5f3f3e3f18,0xbf7ebcc9bf753ec4,0xbf13bf42bf5cbedb,
0x3d973f7c3ef13f55,0xbf313f4abeac3f78,0xbe89bf6fbf22bf35,0x3f09bf653e16bf80,0xbea13f7a3dc93f7b,0xbf6a3efcbf2c3f4e,0x3dfbbf80be95bf6d,0x3f51bf273f04bf67,
0xbe16bf71bf0ebf35,0x3f2cbf5c3e95bf7f,0xbe793f803e483f6d,0xbf673f18bf223f62,0xbf4ebedbbf7b0000,0xbd49bf78bef1bf46,0x3f043f3e3f553ec4,0xbeac3f7d3dc93f75,
0x3f7dbeac3f55bf35,0x3f3e3f043f753dc9,0xbf78bd49bf7b3ec4,0xbedbbf4ebf46bef1,0x3f18bf673e48bf80,0x3f80be793f62bf22,0xbf5c3f2cbf0e3f6d,0xbf71be16bf7f3e95,
0xbf7c3dfbbf753f0e,0xbee6bf39bf4ebeac,0x3f6abf273f22bf6d,0x3f5f3e603f80be79,0xbf093f77bdc93f7b,0xbf7f3eb8bf5c3f3e,0xbcc9bf73bef1bf35,0x3f4abf513edbbf7d,
0x3e2fbf7ebe95bf55,0x3f65bf313f18bf71,0x3ecf3f423f463ec4,0xbefc3f7abd493f78,0xbf58be89bf7f3e48,0xbd97bf6fbf04bf2c,0x3f80bea13f62bf35,0x3f1d3f133f673e16,
0x3f46bf623ec4bf80,0x3f75bdc93f7bbf0e,0xbf7f3e95bf6d3f35,0xbef1bf22bf55be48,0x3f223ef13f6d0000,0xbe953f7f3e483f55,0x3dc9bf75bec4bf35,0x3f62bf463f0ebf7b,
0x3f223ef13f6d8000,0xbe953f7f3e483f55,0x3dc9bf75bec4bf35,0x3f62bf463f0ebf7b,0xbf463f62bec43f80,0xbf753dc9bf7b3f0e,0x3f7fbe953f6dbf35,0x3ef13f223f553e48,
0xbeb8bf27bf46be48,0x3f1dbf7c3e16bf71,0x3f7abe893f75bf35,0x3ea13f313f3e3e79,0x3f80bee63f62bf55,0x3efc3f093f5c3d49,0xbf133f7ebdc93f6d,0xbf7f3ecfbf673f4e,
0x3f6fbf423f22bf7b,0x3f4a3e2f3f7dbeac,0xbe603f773e953f35,0xbf733f39bf2c3f78,0xbcc93f653ef13f0e,0xbf5f3f58bf043f80,0xbf51bdfbbf7f3ec4,0x3d97bf6abedbbf18,
0xbf713e79bf7b3f35,0xbe16bf3ebf22be95,0x3d493f4e3f0e3ec4,0xbf5c3f67bef13f7f,0x3edb3f043f550000,0xbf183f80bdc93f62,0x3f2cbf7d3e48bf6d,0x3f78beac3f75bf46,
0x3eacbf78be48bf35,0x3f7dbf2c3f46bf75,0xbf803f18bf553f6d,0xbf04bedbbf623dc9,0xbf673f5cbf0e3f80,0xbf4ebd49bf7f3ef1,0x3f3e3e163f7bbec4,0xbe793f713e953f22,
0xbf7e3f39bf463f7b,0xbf09bea1bf673e79,0x3d97bf51bef1bec4,0x3f6fbf5f3f18bf80,0x3f77becf3f75bf55,0x3e2f3f273f2c3e16,0xbee63f7a3dc93f35,0xbf803f1dbf5c3f71,
0xbdfbbf31bf22be48,0x3f58bf733edbbf78,0x3f7fbf133f62bf6d,0x3eb83efc3f4ebd49,0xbe893f6a3e953f0e,0xbf7c3f42bf3e3f7d,0xbf653e60bf7f3f35,0x3cc9bf4abf04beac,
0xbf7b3f55bf353f80,0xbf0ebe48bf6d3ec4,0x3e483f0e3f350000,0xbf553f7bbec43f6d,0x3f7bbf553f35bf80,0x3f0e3e483f6dbec4,0xbe48bf0ebf350000,0x3f55bf7b3ec4bf6d,
0xbe48bf0ebf358000,0x3f55bf7b3ec4bf6d,0xbf7b3f55bf353f80,0xbf0ebe48bf6d3ec4,0x3e483f0e3f358000,0xbf553f7bbec43f6d,0x3f7bbf553f35bf80,0x3f0e3e483f6dbec4,
0xbf4a3f80be953f55,0xbf583ea1bf803f4e,0xbf423e2fbf7f3f35,0x3eb8bf5fbe79bedb,0x3f77bf6a3f22bf7b,0x3f133d973f71bf04,0x3ee63e603f62bec4,0xbf313f7ebe163f3e,
0xbf1dbcc9bf753f0e,0x3f09bf73bd49bf18,0x3f27bf7c3dc9bf35,0x3f6fbefc3f78bf67,0x3e893ecf3f46be48,0xbf513f7fbeac3f5c,0xbf653f7abef13f6d,0xbf393dfbbf7d3f2c,
0xbf3e3f7dbe483f35,0xbf5c3edbbf7f3f62,0x3eac3e793f55bec4,0xbf4e3f80be953f46,0x3d49bf18bf0e0000,0x3f78bf713f22bf75,0xbf673f04bf7b3f6d,0x3e16bf2cbef1bdc9,
0xbf2c3e16bf7b3f35,0x3f04bf67bdc9bef1,0xbf713f78bf0e3f6d,0xbf183d49bf753f22,0x3f80bf4e3f55bf80,0x3e793eac3f46be95,0x3edbbf5cbe48bec4,0x3f7dbf3e3f62bf7f,
0xbf6a3f7fbef13f55,0xbf1d3e2fbf783f3e,0xbf583efcbf7f3f6d,0x3ea1bf39beacbe16,0xbcc9bee6bf223e48,0x3f77bf7a3f18bf67,0x3f51bf7e3e95bf35,0x3f42beb83f80bf5c,
0xbecfbd97bf623f0e,0x3f4abf7c3e79bf2c,0x3f09bf5fbdc9bec4,0x3f73bf313f71bf7d,0x3f80bf653f46bf7b,0x3e893e603f4ebedb,0x3f13bdfb3f75bf35,0xbf273f6fbd493f04,
0x3f75bf463f6dbf80,0xbdc93ef13f0ebe48,0x3f62bf7f3ec4bf35,0x3f22be953f7bbf55,0x3e95bf22bec40000,0x3f7fbf623f55bf7b,0xbef13dc9bf6d3f35,0x3f46bf753e48bf0e,
0xbe953f223ec48000,0xbf7f3f62bf553f7b,0x3ef1bdc93f6dbf35,0xbf463f75be483f0e,0x3f75bf463f6dbf80,0xbdc93ef13f0ebe48,0x3f62bf7f3ec4bf35,0x3f22be953f7bbf55,
0x3f51bf1d3f7fbf7b,0xbee63f313e793d49,0x3eb8bd973f62bf35,0xbf5f3f7abeac3f18,0x3f58bf773e95bf0e,0x3f27becf3f7dbf67,0x3f80bf733f46bf6d,0x3dfb3e2f3f3ebf04,
0xbf133f4a3dc93e48,0xbf653f39bf783f80,0xbf6f3f7fbef13f35,0xbefc3e60bf713f4e,0x3f09be893f75bf55,0xbf423f6abe163edb,0xbcc93ea13f22bec4,0xbf7e3f7cbf2c3f5c,
0x3e79bd493f55bf35,0xbf713f7dbef13f22,0x3f18bedb3f7bbf6d,0xbf3e3f5cbdc93e95,0xbf043f2c3e480000,0xbf673f4ebf753f7f,0xbe163eac3f0ebec4,0xbf803f78bf463f62,
0xbf783f80bf0e3f35,0xbeac3e16bf623f46,0xbf4e3f67be483ec4,0xbf2c3f04bf7f3f75,0xbf5c3f3ebf7b3f80,0x3edbbf18be953dc9,0xbf7d3f71bf553f6d,0x3d49be79bf223ef1,
0xbf423f51bdc93e48,0xbf313f1dbf803f7d,0xbf5f3f6abe953ec4,0xbf093ee6bf783f71,0xbf733f7abef13f0e,0xbeb83e89bf673f5c,0xbf7e3f80bf223f35,0xbe2f3d97bf4e3f3e,
0xbf273f13bf7f3f7b,0x3f39bf4a3d49be16,0xbefc3ecfbf753f6d,0x3f58bf653e79beac,0xbea13e60bf623f55,0x3f6fbf773edbbf04,0xbdfb3cc9bf463f35,0x3f7cbf7f3f18bf2c,
0x3f003f003f003f00,0x3f003f003f003f00,0x3f003f003f003f00,0x3f003f003f003f00,0x3f003f003f003f00,0x3f003f003f003f00,0x3f003f003f003f00,0x3f003f003f003f00,
0xbf00bf003f003f00,0xbf00bf003f003f00,0xbf00bf003f003f00,0xbf00bf003f003f00,0xbf00bf003f003f00,0xbf00bf003f003f00,0xbf00bf003f003f00,0xbf00bf003f003f00,
0xbea1be60be95be48,0xbeb8be89beacbe79,0xbdfbbcc9bdc90000,0xbe2fbd97be16bd49,0xbf27bf13bf22bf0e,0xbf31bf1dbf2cbf18,0xbefcbecfbef1bec4,0xbf09bee6bf04bedb,
0xbf73bf7abf75bf7b,0xbf6fbf77bf71bf78,0xbf7ebf80bf7fbf80,0xbf7cbf7fbf7dbf80,0xbf42bf51bf46bf55,0xbf39bf4abf3ebf4e,0xbf5fbf6abf62bf6d,0xbf58bf65bf5cbf67,
0xbf04bf2cbf0ebf35,0xbedbbf18bef1bf22,0xbe16beacbe48bec4,0xbd49be79bdc9be95,0xbf78bf80bf7bbf80,0xbf71bf7dbf75bf7f,0xbf4ebf67bf55bf6d,0xbf3ebf5cbf46bf62,
0x3f5c3f3e3f553f35,0x3f673f4e3f623f46,0x3f7d3f713f7b3f6d,0x3f803f783f7f3f75,0x3e793d493e488000,0x3eac3e163e953dc9,0x3f183edb3f0e3ec4,0x3f2c3f043f223ef1,
0x3f583f773f623f7b,0x3f423f6a3f4e3f71,0x3f803f733f7f3f6d,0x3f7e3f7c3f803f78,0x3f513f1d3f463f0e,0x3f653f393f5c3f2c,0x3eb83d973e950000,0x3efc3e603edb3e16,
0xbf09be89bef1be48,0xbf27becfbf18beac,0x3cc93ea13dc93ec4,0xbdfb3e2fbd493e79,0x3f133f4a3f223f55,0x3ee63f313f043f3e,0x3f6f3f7f3f753f80,0x3f5f3f7a3f673f7d,
0x3f623f7f3f6d3f80,0x3f463f753f553f7b,0x3e953f223ec43f35,0x3dc93ef13e483f0e,0xbef1bdc9bec40000,0xbf22be95bf0ebe48,0xbf75bf46bf6dbf35,0xbf7fbf62bf7bbf55,
0xbef1bdc9bec48000,0xbf22be95bf0ebe48,0xbf75bf46bf6dbf35,0xbf7fbf62bf7bbf55,0xbf62bf7fbf6dbf80,0xbf46bf75bf55bf7b,0xbe95bf22bec4bf35,0xbdc9bef1be48bf0e,
0xbf80bf65bf7fbf55,0xbf77bf7abf7dbf71,0xbf13bdfbbef10000,0xbf42beb8bf2cbe79,0x3ecfbd973e95be48,0x3f1d3e2f3f043d49,0xbf09bf5fbf22bf6d,0xbea1bf39bedbbf4e,
0x3cc9bee6bdc9bf0e,0x3e89be603e16beac,0xbf51bf7ebf62bf80,0xbf27bf6fbf3ebf78,0x3f6a3f7f3f753f7b,0x3f4a3f7c3f5c3f80,0x3f583efc3f463ec4,0x3f733f313f673f18,
0x3f803f4e3f7b3f35,0x3f783f713f7f3f62,0x3edb3f5c3f0e3f6d,0x3e163f2c3e953f46,0xbf3ebf7dbf55bf80,0xbf04bf67bf22bf75,0x3eacbe793e48bec4,0x3f183d493ef1bdc9,
0x3d493f183e483f35,0xbe793eacbdc93ef1,0xbf67bf04bf55bec4,0xbf7dbf3ebf75bf22,0x3f2c3e163f0e8000,0x3f5c3edb3f463e95,0x3f713f783f7b3f6d,0x3f4e3f803f623f7f,
0xbf77bf6abf7fbf55,0xbf51bf7fbf67bf78,0xbee63e60be953ec4,0xbf39bdfbbf183d49,0x3f4a3f803f623f7b,0x3f093f733f2c3f7d,0x3f423e2f3f220000,0x3f6f3efc3f5c3eac,
0x3e89becf3dc9bf0e,0x3f13bd973edbbe79,0xbf65bf7abf75bf6d,0xbf31bf7ebf4ebf80,0xbf1d3cc9bef13e48,0xbf58bea1bf3ebe16,0x3f273f7c3f463f80,0x3eb83f5f3f043f71,
0x3f0e3f7b3f353f80,0x3e483f553ec43f6d,0xbf55be48bf350000,0xbf7bbf0ebf6dbec4,0xbf0ebf7bbf35bf80,0xbe48bf55bec4bf6d,0x3f553e483f350000,0x3f7b3f0e3f6d3ec4,
0xbf55be48bf358000,0xbf7bbf0ebf6dbec4,0xbf0ebf7bbf35bf80,0xbe48bf55bec4bf6d,0x3f553e483f358000,0x3f7b3f0e3f6d3ec4,0x3f0e3f7b3f353f80,0x3e483f553ec43f6d,
0xbe89bf6abef1bf7b,0x3e2fbf27bd49bf4e,0xbf65be60bf460000,0xbf80bf1dbf78bedb,0xbdfb3f313dc93f55,0xbf093ea1beac3f04,0x3f7f3f133f753ec4,0x3f6f3f5f3f7d3f3e,
0x3f773ecf3f623e48,0x3f7c3f423f803f18,0xbee6bf7abf22bf80,0xbcc9bf4abe79bf67,0xbf7ebf39bf7fbf0e,0xbf58bf73bf71bf5c,0x3d973f513e953f6d,0xbeb83efcbe163f2c,
0xbedb3f04be483f35,0xbf4e3d49bf223e95,0xbf2cbf7dbf55bf6d,0xbe79bf71bef1bf7f,0xbeacbf78bf0ebf80,0x3e16bf3ebdc9bf62,0x3f803f183f7b3ec4,0x3f5c3f673f753f46,
0xbf67bf5cbf7bbf35,0xbf18bf80bf46bf75,0x3f3ebe163f0ebec4,0x3f783eac3f623dc9,0x3f713e793f558000,0x3f7d3f2c3f7f3ef1,0xbd493f4e3e483f6d,0xbf043edbbe953f22,
0x3f803ee63f753e48,0x3f5f3f583f783f2c,0xbf13bf7ebf46bf6d,0xbd97bf6abeacbf7d,0xbeb83f27bdc93f55,0xbf4a3e2fbf183edb,0x3f7a3e893f620000,0x3f733f393f803f04,
0x3cc93f653e953f7b,0xbefc3f09be793f3e,0x3f51bdfb3f22bec4,0x3f7f3ecf3f713e16,0xbf6fbf42bf7fbf0e,0xbf1dbf7cbf4ebf67,0x3e603f773ef13f80,0xbea13f31bd493f5c,
0x3dc93f753ec43f80,0xbef13f22be483f55,0xbf46bf62bf6dbf35,0xbe95bf7fbf0ebf7b,0x3f7f3e953f6d0000,0x3f623f463f7b3f0e,0xbf223ef1bec43f35,0xbf75bdc9bf553e48,
0xbf7fbe95bf6d8000,0xbf62bf46bf7bbf0e,0x3f22bef13ec4bf35,0x3f753dc93f55be48,0x3dc93f753ec43f80,0xbef13f22be483f55,0xbf46bf62bf6dbf35,0xbe95bf7fbf0ebf7b,
0x3f58be893f22bf0e,0x3f7f3eb83f783d49,0xbf80bea1bf750000,0xbf4abf51bf71bf18,0xbe2fbf7ebef1bf7b,0x3ee6bf393e16bf67,0xbecf3f42bdc93f6d,0xbf5f3e60bf2c3f04,
0x3f093f773f463f55,0xbd973f6f3e793f80,0x3cc9bf73be95bf80,0x3f1dbf133eacbf4e,0x3f7c3dfb3f62be48,0x3f653f313f7d3edb,0xbf6abf27bf7fbec4,0xbefcbf7abf3ebf5c,
0xbf18bf67bf55bf35,0x3d49bf78be95bf7f,0x3f5c3f2c3f7b3ec4,0x3eac3f7d3f223f62,0x3e16bf71be48bf80,0x3f3ebf043ef1bf46,0x3e793f803f0e3f6d,0xbedb3f4ebdc93f75,
0x3f4ebedb3f0ebf35,0x3f803e793f75bdc9,0xbf043f3ebe483f6d,0xbf713e16bf463ef1,0x3f7d3eac3f7b8000,0x3f2c3f5c3f623f22,0xbf783d49bf553ec4,0xbf67bf18bf7fbe95,
0xbf733e60bf463f0e,0xbf6abefcbf80be16,0x3f7ebcc93f62bec4,0x3f513f273f783eac,0xbf7fbe2fbf753e48,0xbf31bf4abf67bf04,0x3f773eb83f7f0000,0x3f093f653f4e3f2c,
0xbea1bf7abf22bf55,0x3ecfbf5f3d49bf7d,0x3dfb3f803ef13f6d,0xbf133f42be793f71,0x3d97bf7cbe95bf7b,0x3f39bf1d3edbbf5c,0xbe893f6f3dc93f80,0xbf583ee6bf183f3e,
0xbec43f6d00003f80,0xbf6d3ec4bf353f35,0x3ec4bf6d0000bf80,0x3f6dbec43f35bf35,0xbec43f6d00003f80,0xbf6d3ec4bf353f35,0x3ec4bf6d0000bf80,0x3f6dbec43f35bf35,
0xbf6dbec4bf808000,0xbec4bf6dbf35bf35,0x3f6d3ec43f808000,0x3ec43f6d3f353f35,0xbf6dbec4bf808000,0xbec4bf6dbf35bf35,0x3f6d3ec43f808000,0x3ec43f6d3f353f35,
0x3f423f133f753e48,0x3cc93f7e3edb3f5c,0xbf5fbecfbf7f0000,0xbe60bf73bf18bf3e,0x3ee63f583f463f0e,0xbeb83f773d493f7d,0xbf1dbf39bf62bec4,0x3e2fbf7fbe79bf71,
0xbf273f51be953f7b,0xbf803dfbbf673f04,0x3efcbf6a3dc9bf80,0x3f7abea13f4ebf2c,0xbf653f09bf223f55,0xbf6fbe89bf803e16,0x3f4abf313ef1bf6d,0x3f7c3d973f78beac,
0x3f7dbeac3f55bf35,0x3f3e3f043f753dc9,0xbf78bd49bf7b3ec4,0xbedbbf4ebf46bef1,0x3f18bf673e48bf80,0x3f80be793f62bf22,0xbf5c3f2cbf0e3f6d,0xbf71be16bf7f3e95,
0x3e163f713f0e3f35,0xbf2c3f5cbe953f7f,0x3e79bf80be48bf6d,0x3f67bf183f22bf62,0x3f4e3edb3f7b8000,0x3d493f783ef13f46,0xbf04bf3ebf55bec4,0x3eacbf7dbdc9bf75,
0x3f51bf4a3ef1bf7b,0x3f733cc93f7dbedb,0xbeb83f7f3dc93f6d,0xbf773f09bf3e3f5c,0xbe60bf5fbf22bf0e,0x3f27bf6a3e79bf80,0x3f393ee63f750000,0xbdfb3f7c3eac3f4e,
0x3f133f1d3f623e48,0xbea13f803e163f67,0xbf6fbd97bf7f3ec4,0xbe89bf58bf2cbf04,0x3f7abefc3f46bf55,0x3f423ecf3f78bd49,0xbf313f65be953f80,0xbf7e3e2fbf713f18,
0xbf463f62bec43f80,0xbf753dc9bf7b3f0e,0x3f7fbe953f6dbf35,0x3ef13f223f553e48,0xbf22bef1bf6d0000,0x3e95bf7fbe48bf55,0xbdc93f753ec43f35,0xbf623f46bf0e3f7b,
0xbf22bef1bf6d8000,0x3e95bf7fbe48bf55,0xbdc93f753ec43f35,0xbf623f46bf0e3f7b,0x3f46bf623ec4bf80,0x3f75bdc93f7bbf0e,0xbf7f3e95bf6d3f35,0xbef1bf22bf55be48,
0xbecf3f7f3dc93f55,0xbf7e3f13bf4e3f67,0xbf09befcbf620000,0x3ee6bf80bd49bf5c,0xbf31bea1bf753e48,0x3e89bf7abe79bf3e,0x3f7cbf1d3f46bf6d,0x3f273eb83f71be16,
0xbf6a3d97bf7f3f0e,0xbdfbbf51bf18bedb,0x3f58bf5f3ef1bf80,0x3f65bcc93f80bf04,0x3f39bf733e95bf7b,0x3f77be603f78bf2c,0x3e2f3f4a3f223ec4,0xbf423f6fbeac3f7d,
0xbeac3f783e483f35,0xbf7d3f2cbf463f75,0x3f80bf183f55bf6d,0x3f043edb3f62bdc9,0x3f67bf5c3f0ebf80,0x3f4e3d493f7fbef1,0xbf3ebe16bf7b3ec4,0x3e79bf71be95bf22,
0xbf713e79bf7b3f35,0xbe16bf3ebf22be95,0x3d493f4e3f0e3ec4,0xbf5c3f67bef13f7f,0x3edb3f043f558000,0xbf183f80bdc93f62,0x3f2cbf7d3e48bf6d,0x3f78beac3f75bf46,
0xbf1d3f80bdc93f55,0xbf7a3ee6bf713f5c,0xbf27be2fbf753ec4,0x3ecfbf77be16bf2c,0x3f5fbf6f3ef1bf7b,0x3f51bd973f80bf18,0x3ea13f093f460000,0xbf393f7ebe793f67,
0xbf4a3cc9bf7f3f0e,0x3e60bf65beacbf04,0x3f42bf7c3e95bf6d,0x3f6abe893f7dbf3e,0x3efc3eb83f62be48,0xbf133f7fbd493f4e,0xbf733f58bf223f80,0xbf31bdfbbf783edb,
0xbf7b3f55bf353f80,0xbf0ebe48bf6d3ec4,0x3e483f0e3f350000,0xbf553f7bbec43f6d,0x3f7bbf553f35bf80,0x3f0e3e483f6dbec4,0xbe48bf0ebf350000,0x3f55bf7b3ec4bf6d,
0xbe48bf0ebf358000,0x3f55bf7b3ec4bf6d,0xbf7b3f55bf353f80,0xbf0ebe48bf6d3ec4,0x3e483f0e3f358000,0xbf553f7bbec43f6d,0x3f7bbf553f35bf80,0x3f0e3e483f6dbec4,
0xbf7e3f31bf623f7b,0xbe60bee6bf3e3e16,0xbd97bf13bf220000,0x3f6abf773f04bf71,0x3f5fbeb83f7fbf55,0xbe2f3f423edb3e79,0xbea13f583e953ec4,0xbf803f4abf4e3f80,
0x3dfbbf39bef1be48,0x3f7abf653f2cbf7d,0x3f7fbf513f46bf80,0x3ecf3e893f5cbeac,0xbefc3f6f3dc93f0e,0xbf7c3f27bf673f78,0xbf733f09bf753f6d,0xbcc9bf1dbf18bd49,
0xbf2c3e16bf7b3f35,0x3f04bf67bdc9bef1,0xbf713f78bf0e3f6d,0xbf183d49bf753f22,0x3f80bf4e3f55bf80,0x3e793eac3f46be95,0x3edbbf5cbe48bec4,0x3f7dbf3e3f62bf7f,
0x3f3ebf7d3e48bf35,0x3f5cbedb3f7fbf62,0xbeacbe79bf553ec4,0x3f4ebf803e95bf46,0xbd493f183f0e8000,0xbf783f71bf223f75,0x3f67bf043f7bbf6d,0xbe163f2c3ef13dc9,
0x3eb8bf42be95be48,0x3f7ebf513f5cbf80,0x3f7abf773f22bf6d,0x3ee63cc93f67bf18,0x3f39bea13f7fbf55,0xbefc3f583e163eac,0xbe2f3f1d3ef10000,0xbf7f3f6abf3e3f78,
0x3f6fbf273f75bf7b,0xbdfb3f133f04bd49,0x3e603e893f46bec4,0xbf653f80bedb3f4e,0xbf313f73bdc93f0e,0xbf5f3f09bf7d3f71,0xbf7c3f4abf623f80,0xbd97becfbf2c3e79,
0xbf753f46bf6d3f80,0x3dc9bef1bf0e3e48,0xbf623f7fbec43f35,0xbf223e95bf7b3f55,0xbe953f223ec40000,0xbf7f3f62bf553f7b,0x3ef1bdc93f6dbf35,0xbf463f75be483f0e,
0x3e95bf22bec48000,0x3f7fbf623f55bf7b,0xbef13dc9bf6d3f35,0x3f46bf753e48bf0e,0xbf753f46bf6d3f80,0x3dc9bef1bf0e3e48,0xbf623f7fbec43f35,0xbf223e95bf7b3f55,
0xbe2fbdfbbf463f0e,0x3f73bf803f04bf3e,0x3ecfbf27be950000,0x3f77bf583f67bf7d,0xbf7a3f5fbf623f7b,0x3d97beb8bf183eac,0xbf313ee6bf7f3f6d,0x3f1dbf51bd49be79,
0x3f7cbf7e3f22bf55,0x3ea1bcc93f5cbf2c,0x3f6abf423f75bf80,0xbe893f093edbbe16,0x3e60befcbef13e48,0x3f7fbf6f3f4ebf71,0x3f39bf653dc9bec4,0x3f4abf133f80bf78,
0x3f78bf803f0ebf35,0x3eacbe163f62bf46,0x3f4ebf673e48bec4,0x3f2cbf043f7fbf75,0x3f5cbf3e3f7bbf80,0xbedb3f183e95bdc9,0x3f7dbf713f55bf6d,0xbd493e793f22bef1,
0x3e79bd493f55bf35,0xbf713f7dbef13f22,0x3f18bedb3f7bbf6d,0xbf3e3f5cbdc93e95,0xbf043f2c3e488000,0xbf673f4ebf753f7f,0xbe163eac3f0ebec4,0xbf803f78bf463f62,
0xbd973e2f3f22bf0e,0xbf803f7ebf3e3f4e,0xbe893eb83ef1bec4,0xbf7a3f73bf5c3f67,0xbee63f093e95be48,0xbf6a3f5fbf713f78,0xbf1d3f313dc90000,0xbf513f42bf7d3f80,
0xbf7f3f7cbf463f55,0x3cc9bdfbbf2c3f18,0xbf773f6fbf623f6d,0x3e60bea1bf043edb,0xbf653f58bf753f7b,0x3ecfbefcbeac3e79,0xbf4a3f39bf7f3f80,0x3f13bf27be163d49,
0x3f003f003f003f00,0x3f003f003f003f00,0x3f003f003f003f00,0x3f003f003f003f00,0x3f003f003f003f00,0x3f003f003f003f00,0x3f003f003f003f00,0x3f003f003f003f00,
0xbf00bf003f003f00,0xbf00bf003f003f00,0xbf00bf003f003f00,0xbf00bf003f003f00,0xbf00bf003f003f00,0xbf00bf003f003f00,0xbf00bf003f003f00,0xbf00bf003f003f00,
0xbf65bf58bf62bf55,0xbf6abf5fbf67bf5c,0xbf4abf39bf46bf35,0xbf51bf42bf4ebf3e,0xbf7fbf7cbf7fbf7b,0xbf80bf7ebf80bf7d,0xbf77bf6fbf75bf6d,0xbf7abf73bf78bf71,
0xbee6bf09bef1bf0e,0xbecfbefcbedbbf04,0xbf1dbf31bf22bf35,0xbf13bf27bf18bf2c,0xbd97be2fbdc9be48,0xbcc9bdfbbd49be16,0xbe89beb8be95bec4,0xbe60bea1be79beac,
0x3f5c3f3e3f553f35,0x3f673f4e3f623f46,0x3f7d3f713f7b3f6d,0x3f803f783f7f3f75,0x3e793d493e480000,0x3eac3e163e953dc9,0x3f183edb3f0e3ec4,0x3f2c3f043f223ef1,
0x3f043f2c3f0e3f35,0x3edb3f183ef13f22,0x3e163eac3e483ec4,0x3d493e793dc93e95,0x3f783f803f7b3f80,0x3f713f7d3f753f7f,0x3f4e3f673f553f6d,0x3f3e3f5c3f463f62,
0xbf7abf5fbf75bf55,0xbf7fbf6fbf7dbf67,0xbf31bee6bf22bec4,0xbf4abf13bf3ebf04,0xbe2f3dfbbdc93e48,0xbea1bcc9be793d49,0x3ecf3f273ef13f35,0x3e893f093eac3f18,
0xbe60befcbe95bf0e,0xbd97beb8be16bedb,0xbf39bf65bf46bf6d,0xbf1dbf51bf2cbf5c,0xbf7cbf7ebf7fbf7b,0xbf73bf80bf78bf80,0xbf6abf42bf62bf35,0xbf77bf58bf71bf4e,
0xbf62bf7fbf6dbf80,0xbf46bf75bf55bf7b,0xbe95bf22bec4bf35,0xbdc9bef1be48bf0e,0x3ef13dc93ec40000,0x3f223e953f0e3e48,0x3f753f463f6d3f35,0x3f7f3f623f7b3f55,
0x3ef13dc93ec48000,0x3f223e953f0e3e48,0x3f753f463f6d3f35,0x3f7f3f623f7b3f55,0x3f623f7f3f6d3f80,0x3f463f753f553f7b,0x3e953f223ec43f35,0x3dc93ef13e483f0e,
0x3f313f733f463f7b,0x3efc3f583f183f67,0x3f7c3f4a3f753f35,0x3f7f3f6a3f803f5c,0xbf6fbf27bf62bf0e,0xbf7ebf51bf78bf3e,0xbe603e89bdc93ec4,0xbee63cc9beac3e16,
0xbf39bea1bf22be48,0xbf5fbf09bf4ebedb,0x3e2f3f1d3e953f35,0xbd973ecf3d493f04,0xbeb8bf42bef1bf55,0xbdfbbf13be79bf2c,0xbf7abf77bf7fbf6d,0xbf65bf80bf71bf7d,
0xbd49bf18be48bf35,0x3e79beac3dc9bef1,0x3f673f043f553ec4,0x3f7d3f3e3f753f22,0xbf2cbe16bf0e0000,0xbf5cbedbbf46be95,0xbf71bf78bf7bbf6d,0xbf4ebf80bf62bf7f,
0x3f803f4e3f7b3f35,0x3f783f713f7f3f62,0x3edb3f5c3f0e3f6d,0x3e163f2c3e953f46,0xbf3ebf7dbf55bf80,0xbf04bf67bf22bf75,0x3eacbe793e48bec4,0x3f183d493ef1bdc9,
0xbf5fbeb8bf46be48,0xbf7cbf27bf71bf04,0x3ea13f583ef13f6d,0xbcc93f1d3e163f3e,0x3f7e3f313f753f0e,0x3f7a3f653f803f4e,0x3d97bf13bdc9bf35,0x3ecfbe893e79bedb,
0xbefcbf6fbf22bf7b,0xbe2fbf42beacbf5c,0xbf73bf09bf62bec4,0xbf80bf4abf7dbf2c,0x3dfb3f393e953f55,0xbe603ee6bd493f18,0x3f7f3f513f7f3f35,0x3f6a3f773f783f67,
0x3f0e3f7b3f353f80,0x3e483f553ec43f6d,0xbf55be48bf350000,0xbf7bbf0ebf6dbec4,0xbf0ebf7bbf35bf80,0xbe48bf55bec4bf6d,0x3f553e483f350000,0x3f7b3f0e3f6d3ec4,
0xbf55be48bf358000,0xbf7bbf0ebf6dbec4,0xbf0ebf7bbf35bf80,0xbe48bf55bec4bf6d,0x3f553e483f358000,0x3f7b3f0e3f6d3ec4,0x3f0e3f7b3f353f80,0x3e483f553ec43f6d,
0x3efcbeb83e95bf0e,0x3f513d973f2cbe16,0xbf73bf58bf7fbf35,0xbf39bf7ebf5cbf71,0xbf4abcc9bf223e48,0xbf7abee6bf67be79,0x3f423f7c3f623f6d,0x3ecf3f773f183f80,
0x3f5f3f6f3f753f55,0x3f133f7f3f3e3f7d,0x3ea1bf093dc9bf35,0x3f31bdfb3f04beac,0xbf1dbf80bf46bf7b,0xbe60bf65bedbbf78,0xbf273e2fbef13ec4,0xbf6abe89bf4ebd49,
0xbf67bf5cbf7bbf35,0xbf18bf80bf46bf75,0x3f3ebe163f0ebec4,0x3f783eac3f623dc9,0x3f713e793f550000,0x3f7d3f2c3f7f3ef1,0xbd493f4e3e483f6d,0xbf043edbbe953f22,
0x3edbbf043e48bf35,0x3f4ebd493f22be95,0x3f2c3f7d3f553f6d,0x3e793f713ef13f7f,0x3eac3f783f0e3f80,0xbe163f3e3dc93f62,0xbf80bf18bf7bbec4,0xbf5cbf67bf75bf46,
0xbf313ea1bef13f0e,0xbf77be60bf5c3d49,0x3f7c3f1d3f7f3ec4,0x3f423f6f3f673f4e,0xbecfbf7fbf22bf7b,0x3dfbbf51be16bf71,0xbf093efcbe953f35,0xbf65bcc9bf3e3e79,
0xbf39bf73bf62bf55,0xbe89bf7abf04bf80,0xbe2f3f4a3dc93f6d,0xbf273eb8bedb3f18,0x3f6a3d973f46be48,0x3f7e3f133f7d3eac,0xbf58bf5fbf75bf35,0xbee6bf80bf2cbf78,
0xbdc9bf75bec4bf80,0x3ef1bf223e48bf55,0x3f463f623f6d3f35,0x3e953f7f3f0e3f7b,0xbf7fbe95bf6d0000,0xbf62bf46bf7bbf0e,0x3f22bef13ec4bf35,0x3f753dc93f55be48,
0x3f7f3e953f6d8000,0x3f623f463f7b3f0e,0xbf223ef1bec43f35,0xbf75bdc9bf553e48,0xbdc9bf75bec4bf80,0x3ef1bf223e48bf55,0x3f463f623f6d3f35,0x3e953f7f3f0e3f7b,
0xbf7abefcbf7fbe48,0xbf27bf6abf5cbf3e,0x3f313f653f623f35,0x3dfb3f7c3edb3f7d,0xbf133f1dbe953f55,0xbf733cc9bf4e3eac,0x3f6fbd973f46bec4,0x3f773f093f803e79,
0x3e60bf5fbdc9bf7b,0x3f42becf3f04bf2c,0xbf393ee6bef13f35,0xbf7ebe2fbf673e16,0xbf51bf4abf75bf0e,0xbea1bf80bf18bf71,0x3eb83f7f3f223f6d,0xbe893f583d493f78,
0xbf4e3edbbf0e3f35,0xbf80be79bf753dc9,0x3f04bf3e3e48bf6d,0x3f71be163f46bef1,0xbf7dbeacbf7b0000,0xbf2cbf5cbf62bf22,0x3f78bd493f55bec4,0x3f673f183f7f3e95,
0xbf18bf67bf55bf35,0x3d49bf78be95bf7f,0x3f5c3f2c3f7b3ec4,0x3eac3f7d3f223f62,0x3e16bf71be48bf80,0x3f3ebf043ef1bf46,0x3e793f803f0e3f6d,0xbedb3f4ebdc93f75,
0xbee63f58bdc93f7b,0xbf6f3e89bf3e3f18,0x3f1dbf393e95bf6d,0x3f7cbd973f5cbedb,0xbf423f13bef13f55,0xbf80bdfbbf713e79,0x3f5fbecf3f22bf35,0x3f7a3ea13f7dbd49,
0xbf65bf09bf7fbe48,0xbeb8bf77bf2cbf4e,0x3f4a3f313f753ec4,0x3e2f3f7f3f043f67,0xbf27bf51bf62bf0e,0x3cc9bf7ebeacbf78,0x3efc3f6a3f463f35,0xbe603f733e163f80,
0xbec43f6d00003f80,0xbf6d3ec4bf353f35,0x3ec4bf6d0000bf80,0x3f6dbec43f35bf35,0xbec43f6d00003f80,0xbf6d3ec4bf353f35,0x3ec4bf6d0000bf80,0x3f6dbec43f35bf35,
0xbf6dbec4bf808000,0xbec4bf6dbf35bf35,0x3f6d3ec43f808000,0x3ec43f6d3f353f35,0xbf6dbec4bf808000,0xbec4bf6dbf35bf35,0x3f6d3ec43f808000,0x3ec43f6d3f353f35,
0x3d973f7c3ef13f55,0xbf313f4abeac3f78,0xbe89bf6fbf22bf35,0x3f09bf653e16bf80,0xbea13f7a3dc93f7b,0xbf6a3efcbf2c3f4e,0x3dfbbf80be95bf6d,0x3f51bf273f04bf67,
0xbf7f3e2fbf623f0e,0xbf39bf1dbf71be79,0x3f77beb83f46bf35,0x3f583ee63f7d3d49,0xbf73be60bf7f3e48,0xbecfbf5fbf3ebf18,0x3f7e3cc93f75bec4,0x3f133f423f5c3edb,
0x3e163f713f0e3f35,0xbf2c3f5cbe953f7f,0x3e79bf80be48bf6d,0x3f67bf183f22bf62,0x3f4e3edb3f7b0000,0x3d493f783ef13f46,0xbf04bf3ebf55bec4,0x3eacbf7dbdc9bf75,
0xbf7d3eacbf553f35,0xbf3ebf04bf75bdc9,0x3f783d493f7bbec4,0x3edb3f4e3f463ef1,0xbf183f67be483f80,0xbf803e79bf623f22,0x3f5cbf2c3f0ebf6d,0x3f713e163f7fbe95,
0xbe2f3f7e3e953f55,0xbf653f31bf183f71,0xbecfbf42bf46bec4,0x3efcbf7a3d49bf78,0x3f583e893f7fbe48,0x3d973f6f3f043f2c,0xbf803ea1bf623f35,0xbf1dbf13bf67be16,
0xbf7c3dfbbf753f0e,0xbee6bf39bf4ebeac,0x3f6abf273f22bf6d,0x3f5f3e603f80be79,0xbf093f77bdc93f7b,0xbf7f3eb8bf5c3f3e,0xbcc9bf73bef1bf35,0x3f4abf513edbbf7d,
0x3f46bf623ec4bf80,0x3f75bdc93f7bbf0e,0xbf7f3e95bf6d3f35,0xbef1bf22bf55be48,0x3f223ef13f6d0000,0xbe953f7f3e483f55,0x3dc9bf75bec4bf35,0x3f62bf463f0ebf7b,
0x3f223ef13f6d8000,0xbe953f7f3e483f55,0x3dc9bf75bec4bf35,0x3f62bf463f0ebf7b,0xbf463f62bec43f80,0xbf753dc9bf7b3f0e,0x3f7fbe953f6dbf35,0x3ef13f223f553e48,
0x3f6fbf423f22bf7b,0x3f4a3e2f3f7dbeac,0xbe603f773e953f35,0xbf733f39bf2c3f78,0xbcc93f653ef13f0e,0xbf5f3f58bf043f80,0xbf51bdfbbf7f3ec4,0x3d97bf6abedbbf18,
0x3eb83f273f463e48,0xbf1d3f7cbe163f71,0xbf7a3e89bf753f35,0xbea1bf31bf3ebe79,0xbf803ee6bf623f55,0xbefcbf09bf5cbd49,0x3f13bf7e3dc9bf6d,0x3f7fbecf3f67bf4e,
0x3f71be793f7bbf35,0x3e163f3e3f223e95,0xbd49bf4ebf0ebec4,0x3f5cbf673ef1bf7f,0xbedbbf04bf550000,0x3f18bf803dc9bf62,0xbf2c3f7dbe483f6d,0xbf783eacbf753f46,
0xbeac3f783e483f35,0xbf7d3f2cbf463f75,0x3f80bf183f55bf6d,0x3f043edb3f62bdc9,0x3f67bf5c3f0ebf80,0x3f4e3d493f7fbef1,0xbf3ebe16bf7b3ec4,0x3e79bf71be95bf22,
0x3dfb3f313f223e48,0xbf583f73bedb3f78,0xbf7f3f13bf623f6d,0xbeb8befcbf4e3d49,0x3e89bf6abe95bf0e,0x3f7cbf423f3ebf7d,0x3f65be603f7fbf35,0xbcc93f4a3f043eac,
0xbf7e3f39bf463f7b,0xbf09bea1bf673e79,0x3d97bf51bef1bec4,0x3f6fbf5f3f18bf80,0x3f77becf3f75bf55,0x3e2f3f273f2c3e16,0xbee63f7a3dc93f35,0xbf803f1dbf5c3f71,
0xbf7b3f55bf353f80,0xbf0ebe48bf6d3ec4,0x3e483f0e3f350000,0xbf553f7bbec43f6d,0x3f7bbf553f35bf80,0x3f0e3e483f6dbec4,0xbe48bf0ebf350000,0x3f55bf7b3ec4bf6d,
0xbe48bf0ebf358000,0x3f55bf7b3ec4bf6d,0xbf7b3f55bf353f80,0xbf0ebe48bf6d3ec4,0x3e483f0e3f358000,0xbf553f7bbec43f6d,0x3f7bbf553f35bf80,0x3f0e3e483f6dbec4,
0xbf1dbcc9bf753f0e,0x3f09bf73bd49bf18,0x3f27bf7c3dc9bf35,0x3f6fbefc3f78bf67,0x3e893ecf3f46be48,0xbf513f7fbeac3f5c,0xbf653f7abef13f6d,0xbf393dfbbf7d3f2c,
0x3f4abf803e95bf55,0x3f58bea13f80bf4e,0x3f42be2f3f7fbf35,0xbeb83f5f3e793edb,0xbf773f6abf223f7b,0xbf13bd97bf713f04,0xbee6be60bf623ec4,0x3f31bf7e3e16bf3e,
0x3f3ebf7d3e48bf35,0x3f5cbedb3f7fbf62,0xbeacbe79bf553ec4,0x3f4ebf803e95bf46,0xbd493f183f0e0000,0xbf783f71bf223f75,0x3f67bf043f7bbf6d,0xbe163f2c3ef13dc9,
0x3f2cbe163f7bbf35,0xbf043f673dc93ef1,0x3f71bf783f0ebf6d,0x3f18bd493f75bf22,0xbf803f4ebf553f80,0xbe79beacbf463e95,0xbedb3f5c3e483ec4,0xbf7d3f3ebf623f7f,
0x3ecf3d973f62bf0e,0xbf4a3f7cbe793f2c,0xbf093f5f3dc93ec4,0xbf733f31bf713f7d,0xbf803f65bf463f7b,0xbe89be60bf4e3edb,0xbf133dfbbf753f35,0x3f27bf6f3d49bf04,
0xbf6a3f7fbef13f55,0xbf1d3e2fbf783f3e,0xbf583efcbf7f3f6d,0x3ea1bf39beacbe16,0xbcc9bee6bf223e48,0x3f77bf7a3f18bf67,0x3f51bf7e3e95bf35,0x3f42beb83f80bf5c,
0x3f75bf463f6dbf80,0xbdc93ef13f0ebe48,0x3f62bf7f3ec4bf35,0x3f22be953f7bbf55,0x3e95bf22bec40000,0x3f7fbf623f55bf7b,0xbef13dc9bf6d3f35,0x3f46bf753e48bf0e,
0xbe953f223ec48000,0xbf7f3f62bf553f7b,0x3ef1bdc93f6dbf35,0xbf463f75be483f0e,0x3f75bf463f6dbf80,0xbdc93ef13f0ebe48,0x3f62bf7f3ec4bf35,0x3f22be953f7bbf55,
0xbf133f4a3dc93e48,0xbf653f39bf783f80,0xbf6f3f7fbef13f35,0xbefc3e60bf713f4e,0x3f09be893f75bf55,0xbf423f6abe163edb,0xbcc93ea13f22bec4,0xbf7e3f7cbf2c3f5c,
0xbf513f1dbf7f3f7b,0x3ee6bf31be79bd49,0xbeb83d97bf623f35,0x3f5fbf7a3eacbf18,0xbf583f77be953f0e,0xbf273ecfbf7d3f67,0xbf803f73bf463f6d,0xbdfbbe2fbf3e3f04,
0xbe793d49bf553f35,0x3f71bf7d3ef1bf22,0xbf183edbbf7b3f6d,0x3f3ebf5c3dc9be95,0x3f04bf2cbe480000,0x3f67bf4e3f75bf7f,0x3e16beacbf0e3ec4,0x3f80bf783f46bf62,
0x3f78bf803f0ebf35,0x3eacbe163f62bf46,0x3f4ebf673e48bec4,0x3f2cbf043f7fbf75,0x3f5cbf3e3f7bbf80,0xbedb3f183e95bdc9,0x3f7dbf713f55bf6d,0xbd493e793f22bef1,
0x3f27bf133f7fbf7b,0xbf393f4abd493e16,0x3efcbecf3f75bf6d,0xbf583f65be793eac,0x3ea1be603f62bf55,0xbf6f3f77bedb3f04,0x3dfbbcc93f46bf35,0xbf7c3f7fbf183f2c,
0xbf423f51bdc93e48,0xbf313f1dbf803f7d,0xbf5f3f6abe953ec4,0xbf093ee6bf783f71,0xbf733f7abef13f0e,0xbeb83e89bf673f5c,0xbf7e3f80bf223f35,0xbe2f3d97bf4e3f3e,
0x3f003f003f003f00,0x3f003f003f003f00,0x3f003f003f003f00,0x3f003f003f003f00,0x3f003f003f003f00,0x3f003f003f003f00,0x3f003f003f003f00,0x3f003f003f003f00,
0xbf00bf003f003f00,0xbf00bf003f003f00,0xbf00bf003f003f00,0xbf00bf003f003f00,0xbf00bf003f003f00,0xbf00bf003f003f00,0xbf00bf003f003f00,0xbf00bf003f003f00,
0xbf73bf7abf75bf7b,0xbf6fbf77bf71bf78,0xbf7ebf80bf7fbf80,0xbf7cbf7fbf7dbf80,0xbf42bf51bf46bf55,0xbf39bf4abf3ebf4e,0xbf5fbf6abf62bf6d,0xbf58bf65bf5cbf67,
0x3ea13e603e953e48,0x3eb83e893eac3e79,0x3dfb3cc93dc98000,0x3e2f3d973e163d49,0x3f273f133f223f0e,0x3f313f1d3f2c3f18,0x3efc3ecf3ef13ec4,0x3f093ee63f043edb,
0x3f043f2c3f0e3f35,0x3edb3f183ef13f22,0x3e163eac3e483ec4,0x3d493e793dc93e95,0x3f783f803f7b3f80,0x3f713f7d3f753f7f,0x3f4e3f673f553f6d,0x3f3e3f5c3f463f62,
0xbf5cbf3ebf55bf35,0xbf67bf4ebf62bf46,0xbf7dbf71bf7bbf6d,0xbf80bf78bf7fbf75,0xbe79bd49be488000,0xbeacbe16be95bdc9,0xbf18bedbbf0ebec4,0xbf2cbf04bf22bef1,
0x3f093e893ef13e48,0x3f273ecf3f183eac,0xbcc9bea1bdc9bec4,0x3dfbbe2f3d49be79,0xbf13bf4abf22bf55,0xbee6bf31bf04bf3e,0xbf6fbf7fbf75bf80,0xbf5fbf7abf67bf7d,
0x3f583f773f623f7b,0x3f423f6a3f4e3f71,0x3f803f733f7f3f6d,0x3f7e3f7c3f803f78,0x3f513f1d3f463f0e,0x3f653f393f5c3f2c,0x3eb83d973e958000,0x3efc3e603edb3e16,
0x3f623f7f3f6d3f80,0x3f463f753f553f7b,0x3e953f223ec43f35,0x3dc93ef13e483f0e,0xbef1bdc9bec40000,0xbf22be95bf0ebe48,0xbf75bf46bf6dbf35,0xbf7fbf62bf7bbf55,
0xbef1bdc9bec48000,0xbf22be95bf0ebe48,0xbf75bf46bf6dbf35,0xbf7fbf62bf7bbf55,0xbf62bf7fbf6dbf80,0xbf46bf75bf55bf7b,0xbe95bf22bec4bf35,0xbdc9bef1be48bf0e,
0x3cc9bee6bdc9bf0e,0x3e89be603e16beac,0xbf51bf7ebf62bf80,0xbf27bf6fbf3ebf78,0x3f6a3f7f3f753f7b,0x3f4a3f7c3f5c3f80,0x3f583efc3f463ec4,0x3f733f313f673f18,
0x3f803f653f7f3f55,0x3f773f7a3f7d3f71,0x3f133dfb3ef18000,0x3f423eb83f2c3e79,0xbecf3d97be953e48,0xbf1dbe2fbf04bd49,0x3f093f5f3f223f6d,0x3ea13f393edb3f4e,
0xbf80bf4ebf7bbf35,0xbf78bf71bf7fbf62,0xbedbbf5cbf0ebf6d,0xbe16bf2cbe95bf46,0x3f3e3f7d3f553f80,0x3f043f673f223f75,0xbeac3e79be483ec4,0xbf18bd49bef13dc9,
0xbd49bf18be48bf35,0x3e79beac3dc9bef1,0x3f673f043f553ec4,0x3f7d3f3e3f753f22,0xbf2cbe16bf0e8000,0xbf5cbedbbf46be95,0xbf71bf78bf7bbf6d,0xbf4ebf80bf62bf7f,
0xbe893ecfbdc93f0e,0xbf133d97bedb3e79,0x3f653f7a3f753f6d,0x3f313f7e3f4e3f80,0x3f1dbcc93ef1be48,0x3f583ea13f3e3e16,0xbf27bf7cbf46bf80,0xbeb8bf5fbf04bf71,
0xbf77bf6abf7fbf55,0xbf51bf7fbf67bf78,0xbee63e60be953ec4,0xbf39bdfbbf183d49,0x3f4a3f803f623f7b,0x3f093f733f2c3f7d,0x3f423e2f3f228000,0x3f6f3efc3f5c3eac,
0x3f0e3f7b3f353f80,0x3e483f553ec43f6d,0xbf55be48bf350000,0xbf7bbf0ebf6dbec4,0xbf0ebf7bbf35bf80,0xbe48bf55bec4bf6d,0x3f553e483f350000,0x3f7b3f0e3f6d3ec4,
0xbf55be48bf358000,0xbf7bbf0ebf6dbec4,0xbf0ebf7bbf35bf80,0xbe48bf55bec4bf6d,0x3f553e483f358000,0x3f7b3f0e3f6d3ec4,0x3f0e3f7b3f353f80,0x3e483f553ec43f6d,
0x3f773ecf3f623e48,0x3f7c3f423f803f18,0xbee6bf7abf22bf80,0xbcc9bf4abe79bf67,0xbf7ebf39bf7fbf0e,0xbf58bf73bf71bf5c,0x3d973f513e953f6d,0xbeb83efcbe163f2c,
0x3e893f6a3ef13f7b,0xbe2f3f273d493f4e,0x3f653e603f468000,0x3f803f1d3f783edb,0x3dfbbf31bdc9bf55,0x3f09bea13eacbf04,0xbf7fbf13bf75bec4,0xbf6fbf5fbf7dbf3e,
0x3edbbf043e48bf35,0x3f4ebd493f22be95,0x3f2c3f7d3f553f6d,0x3e793f713ef13f7f,0x3eac3f783f0e3f80,0xbe163f3e3dc93f62,0xbf80bf18bf7bbec4,0xbf5cbf67bf75bf46,
0x3f673f5c3f7b3f35,0x3f183f803f463f75,0xbf3e3e16bf0e3ec4,0xbf78beacbf62bdc9,0xbf71be79bf558000,0xbf7dbf2cbf7fbef1,0x3d49bf4ebe48bf6d,0x3f04bedb3e95bf22,
0xbcc9bf65be95bf7b,0x3efcbf093e79bf3e,0xbf513dfbbf223ec4,0xbf7fbecfbf71be16,0x3f6f3f423f7f3f0e,0x3f1d3f7c3f4e3f67,0xbe60bf77bef1bf80,0x3ea1bf313d49bf5c,
0x3f803ee63f753e48,0x3f5f3f583f783f2c,0xbf13bf7ebf46bf6d,0xbd97bf6abeacbf7d,0xbeb83f27bdc93f55,0xbf4a3e2fbf183edb,0x3f7a3e893f628000,0x3f733f393f803f04,
0x3dc93f753ec43f80,0xbef13f22be483f55,0xbf46bf62bf6dbf35,0xbe95bf7fbf0ebf7b,0x3f7f3e953f6d0000,0x3f623f463f7b3f0e,0xbf223ef1bec43f35,0xbf75bdc9bf553e48,
0xbf7fbe95bf6d8000,0xbf62bf46bf7bbf0e,0x3f22bef13ec4bf35,0x3f753dc93f55be48,0x3dc93f753ec43f80,0xbef13f22be483f55,0xbf46bf62bf6dbf35,0xbe95bf7fbf0ebf7b,
0x3f093f773f463f55,0xbd973f6f3e793f80,0x3cc9bf73be95bf80,0x3f1dbf133eacbf4e,0x3f7c3dfb3f62be48,0x3f653f313f7d3edb,0xbf6abf27bf7fbec4,0xbefcbf7abf3ebf5c,
0xbf583e89bf223f0e,0xbf7fbeb8bf78bd49,0x3f803ea13f758000,0x3f4a3f513f713f18,0x3e2f3f7e3ef13f7b,0xbee63f39be163f67,0x3ecfbf423dc9bf6d,0x3f5fbe603f2cbf04,
0x3f183f673f553f35,0xbd493f783e953f7f,0xbf5cbf2cbf7bbec4,0xbeacbf7dbf22bf62,0xbe163f713e483f80,0xbf3e3f04bef13f46,0xbe79bf80bf0ebf6d,0x3edbbf4e3dc9bf75,
0xbf4e3edbbf0e3f35,0xbf80be79bf753dc9,0x3f04bf3e3e48bf6d,0x3f71be163f46bef1,0xbf7dbeacbf7b8000,0xbf2cbf5cbf62bf22,0x3f78bd493f55bec4,0x3f673f183f7f3e95,
0x3ea13f7a3f223f55,0xbecf3f5fbd493f7d,0xbdfbbf80bef1bf6d,0x3f13bf423e79bf71,0xbd973f7c3e953f7b,0xbf393f1dbedb3f5c,0x3e89bf6fbdc9bf80,0x3f58bee63f18bf3e,
0xbf733e60bf463f0e,0xbf6abefcbf80be16,0x3f7ebcc93f62bec4,0x3f513f273f783eac,0xbf7fbe2fbf753e48,0xbf31bf4abf67bf04,0x3f773eb83f7f8000,0x3f093f653f4e3f2c,
0xbec43f6d00003f80,0xbf6d3ec4bf353f35,0x3ec4bf6d0000bf80,0x3f6dbec43f35bf35,0xbec43f6d00003f80,0xbf6d3ec4bf353f35,0x3ec4bf6d0000bf80,0x3f6dbec43f35bf35,
0xbf6dbec4bf808000,0xbec4bf6dbf35bf35,0x3f6d3ec43f808000,0x3ec43f6d3f353f35,0xbf6dbec4bf808000,0xbec4bf6dbf35bf35,0x3f6d3ec43f808000,0x3ec43f6d3f353f35,
0xbf273f51be953f7b,0xbf803dfbbf673f04,0x3efcbf6a3dc9bf80,0x3f7abea13f4ebf2c,0xbf653f09bf223f55,0xbf6fbe89bf803e16,0x3f4abf313ef1bf6d,0x3f7c3d973f78beac,
0xbf42bf13bf75be48,0xbcc9bf7ebedbbf5c,0x3f5f3ecf3f7f8000,0x3e603f733f183f3e,0xbee6bf58bf46bf0e,0x3eb8bf77bd49bf7d,0x3f1d3f393f623ec4,0xbe2f3f7f3e793f71,
0xbf7d3eacbf553f35,0xbf3ebf04bf75bdc9,0x3f783d493f7bbec4,0x3edb3f4e3f463ef1,0xbf183f67be483f80,0xbf803e79bf623f22,0x3f5cbf2c3f0ebf6d,0x3f713e163f7fbe95,
0xbe16bf71bf0ebf35,0x3f2cbf5c3e95bf7f,0xbe793f803e483f6d,0xbf673f18bf223f62,0xbf4ebedbbf7b8000,0xbd49bf78bef1bf46,0x3f043f3e3f553ec4,0xbeac3f7d3dc93f75,
0xbf13bf1dbf62be48,0x3ea1bf80be16bf67,0x3f6f3d973f7fbec4,0x3e893f583f2c3f04,0xbf7a3efcbf463f55,0xbf42becfbf783d49,0x3f31bf653e95bf80,0x3f7ebe2f3f71bf18,
0x3f51bf4a3ef1bf7b,0x3f733cc93f7dbedb,0xbeb83f7f3dc93f6d,0xbf773f09bf3e3f5c,0xbe60bf5fbf22bf0e,0x3f27bf6a3e79bf80,0x3f393ee63f758000,0xbdfb3f7c3eac3f4e,
0xbf463f62bec43f80,0xbf753dc9bf7b3f0e,0x3f7fbe953f6dbf35,0x3ef13f223f553e48,0xbf22bef1bf6d0000,0x3e95bf7fbe48bf55,0xbdc93f753ec43f35,0xbf623f46bf0e3f7b,
0xbf22bef1bf6d8000,0x3e95bf7fbe48bf55,0xbdc93f753ec43f35,0xbf623f46bf0e3f7b,0x3f46bf623ec4bf80,0x3f75bdc93f7bbf0e,0xbf7f3e95bf6d3f35,0xbef1bf22bf55be48,
0xbf6a3d97bf7f3f0e,0xbdfbbf51bf18bedb,0x3f58bf5f3ef1bf80,0x3f65bcc93f80bf04,0x3f39bf733e95bf7b,0x3f77be603f78bf2c,0x3e2f3f4a3f223ec4,0xbf423f6fbeac3f7d,
0x3ecfbf7fbdc9bf55,0x3f7ebf133f4ebf67,0x3f093efc3f628000,0xbee63f803d493f5c,0x3f313ea13f75be48,0xbe893f7a3e793f3e,0xbf7c3f1dbf463f6d,0xbf27beb8bf713e16,
0x3eacbf78be48bf35,0x3f7dbf2c3f46bf75,0xbf803f18bf553f6d,0xbf04bedbbf623dc9,0xbf673f5cbf0e3f80,0xbf4ebd49bf7f3ef1,0x3f3e3e163f7bbec4,0xbe793f713e953f22,
0x3f71be793f7bbf35,0x3e163f3e3f223e95,0xbd49bf4ebf0ebec4,0x3f5cbf673ef1bf7f,0xbedbbf04bf558000,0x3f18bf803dc9bf62,0xbf2c3f7dbe483f6d,0xbf783eacbf753f46,
0x3f4abcc93f7fbf0e,0xbe603f653eac3f04,0xbf423f7cbe953f6d,0xbf6a3e89bf7d3f3e,0xbefcbeb8bf623e48,0x3f13bf7f3d49bf4e,0x3f73bf583f22bf80,0x3f313dfb3f78bedb,
0xbf1d3f80bdc93f55,0xbf7a3ee6bf713f5c,0xbf27be2fbf753ec4,0x3ecfbf77be16bf2c,0x3f5fbf6f3ef1bf7b,0x3f51bd973f80bf18,0x3ea13f093f468000,0xbf393f7ebe793f67,
0xbf7b3f55bf353f80,0xbf0ebe48bf6d3ec4,0x3e483f0e3f350000,0xbf553f7bbec43f6d,0x3f7bbf553f35bf80,0x3f0e3e483f6dbec4,0xbe48bf0ebf350000,0x3f55bf7b3ec4bf6d,
0xbe48bf0ebf358000,0x3f55bf7b3ec4bf6d,0xbf7b3f55bf353f80,0xbf0ebe48bf6d3ec4,0x3e483f0e3f358000,0xbf553f7bbec43f6d,0x3f7bbf553f35bf80,0x3f0e3e483f6dbec4,
0x3dfbbf39bef1be48,0x3f7abf653f2cbf7d,0x3f7fbf513f46bf80,0x3ecf3e893f5cbeac,0xbefc3f6f3dc93f0e,0xbf7c3f27bf673f78,0xbf733f09bf753f6d,0xbcc9bf1dbf18bd49,
0x3f7ebf313f62bf7b,0x3e603ee63f3ebe16,0x3d973f133f228000,0xbf6a3f77bf043f71,0xbf5f3eb8bf7f3f55,0x3e2fbf42bedbbe79,0x3ea1bf58be95bec4,0x3f80bf4a3f4ebf80,
0x3f2cbe163f7bbf35,0xbf043f673dc93ef1,0x3f71bf783f0ebf6d,0x3f18bd493f75bf22,0xbf803f4ebf553f80,0xbe79beacbf463e95,0xbedb3f5c3e483ec4,0xbf7d3f3ebf623f7f,
0xbf3e3f7dbe483f35,0xbf5c3edbbf7f3f62,0x3eac3e793f55bec4,0xbf4e3f80be953f46,0x3d49bf18bf0e8000,0x3f78bf713f22bf75,0xbf673f04bf7b3f6d,0x3e16bf2cbef1bdc9,
0xbf6f3f27bf753f7b,0x3dfbbf13bf043d49,0xbe60be89bf463ec4,0x3f65bf803edbbf4e,0x3f31bf733dc9bf0e,0x3f5fbf093f7dbf71,0x3f7cbf4a3f62bf80,0x3d973ecf3f2cbe79,
0x3eb8bf42be95be48,0x3f7ebf513f5cbf80,0x3f7abf773f22bf6d,0x3ee63cc93f67bf18,0x3f39bea13f7fbf55,0xbefc3f583e163eac,0xbe2f3f1d3ef18000,0xbf7f3f6abf3e3f78,
0xbf753f46bf6d3f80,0x3dc9bef1bf0e3e48,0xbf623f7fbec43f35,0xbf223e95bf7b3f55,0xbe953f223ec40000,0xbf7f3f62bf553f7b,0x3ef1bdc93f6dbf35,0xbf463f75be483f0e,
0x3e95bf22bec48000,0x3f7fbf623f55bf7b,0xbef13dc9bf6d3f35,0x3f46bf753e48bf0e,0xbf753f46bf6d3f80,0x3dc9bef1bf0e3e48,0xbf623f7fbec43f35,0xbf223e95bf7b3f55,
0x3f7cbf7e3f22bf55,0x3ea1bcc93f5cbf2c,0x3f6abf423f75bf80,0xbe893f093edbbe16,0x3e60befcbef13e48,0x3f7fbf6f3f4ebf71,0x3f39bf653dc9bec4,0x3f4abf133f80bf78,
0x3e2f3dfb3f46bf0e,0xbf733f80bf043f3e,0xbecf3f273e958000,0xbf773f58bf673f7d,0x3f7abf5f3f62bf7b,0xbd973eb83f18beac,0x3f31bee63f7fbf6d,0xbf1d3f513d493e79,
0xbf783f80bf0e3f35,0xbeac3e16bf623f46,0xbf4e3f67be483ec4,0xbf2c3f04bf7f3f75,0xbf5c3f3ebf7b3f80,0x3edbbf18be953dc9,0xbf7d3f71bf553f6d,0x3d49be79bf223ef1,
0xbe793d49bf553f35,0x3f71bf7d3ef1bf22,0xbf183edbbf7b3f6d,0x3f3ebf5c3dc9be95,0x3f04bf2cbe488000,0x3f67bf4e3f75bf7f,0x3e16beacbf0e3ec4,0x3f80bf783f46bf62,
0x3f7fbf7c3f46bf55,0xbcc93dfb3f2cbf18,0x3f77bf6f3f62bf6d,0xbe603ea13f04bedb,0x3f65bf583f75bf7b,0xbecf3efc3eacbe79,0x3f4abf393f7fbf80,0xbf133f273e16bd49,
0xbd973e2f3f22bf0e,0xbf803f7ebf3e3f4e,0xbe893eb83ef1bec4,0xbf7a3f73bf5c3f67,0xbee63f093e95be48,0xbf6a3f5fbf713f78,0xbf1d3f313dc98000,0xbf513f42bf7d3f80,
0x3f003f003f003f00,0x3f003f003f003f00,0x3f003f003f003f00,0x3f003f003f003f00,0x3f003f003f003f00,0x3f003f003f003f00,0x3f003f003f003f00,0x3f003f003f003f00,
0xbf00bf003f003f00,0xbf00bf003f003f00,0xbf00bf003f003f00,0xbf00bf003f003f00,0xbf00bf003f003f00,0xbf00bf003f003f00,0xbf00bf003f003f00,0xbf00bf003f003f00,
0xbee6bf09bef1bf0e,0xbecfbefcbedbbf04,0xbf1dbf31bf22bf35,0xbf13bf27bf18bf2c,0xbd97be2fbdc9be48,0xbcc9bdfbbd49be16,0xbe89beb8be95bec4,0xbe60bea1be79beac,
0x3f653f583f623f55,0x3f6a3f5f3f673f5c,0x3f4a3f393f463f35,0x3f513f423f4e3f3e,0x3f7f3f7c3f7f3f7b,0x3f803f7e3f803f7d,0x3f773f6f3f753f6d,0x3f7a3f733f783f71,
0xbf5cbf3ebf55bf35,0xbf67bf4ebf62bf46,0xbf7dbf71bf7bbf6d,0xbf80bf78bf7fbf75,0xbe79bd49be480000,0xbeacbe16be95bdc9,0xbf18bedbbf0ebec4,0xbf2cbf04bf22bef1,
0xbf04bf2cbf0ebf35,0xbedbbf18bef1bf22,0xbe16beacbe48bec4,0xbd49be79bdc9be95,0xbf78bf80bf7bbf80,0xbf71bf7dbf75bf7f,0xbf4ebf67bf55bf6d,0xbf3ebf5cbf46bf62,
0x3e603efc3e953f0e,0x3d973eb83e163edb,0x3f393f653f463f6d,0x3f1d3f513f2c3f5c,0x3f7c3f7e3f7f3f7b,0x3f733f803f783f80,0x3f6a3f423f623f35,0x3f773f583f713f4e,
0xbf7abf5fbf75bf55,0xbf7fbf6fbf7dbf67,0xbf31bee6bf22bec4,0xbf4abf13bf3ebf04,0xbe2f3dfbbdc93e48,0xbea1bcc9be793d49,0x3ecf3f273ef13f35,0x3e893f093eac3f18,
0xbf62bf7fbf6dbf80,0xbf46bf75bf55bf7b,0xbe95bf22bec4bf35,0xbdc9bef1be48bf0e,0x3ef13dc93ec40000,0x3f223e953f0e3e48,0x3f753f463f6d3f35,0x3f7f3f623f7b3f55,
0x3ef13dc93ec48000,0x3f223e953f0e3e48,0x3f753f463f6d3f35,0x3f7f3f623f7b3f55,0x3f623f7f3f6d3f80,0x3f463f753f553f7b,0x3e953f223ec43f35,0x3dc93ef13e483f0e,
0xbf39bea1bf22be48,0xbf5fbf09bf4ebedb,0x3e2f3f1d3e953f35,0xbd973ecf3d493f04,0xbeb8bf42bef1bf55,0xbdfbbf13be79bf2c,0xbf7abf77bf7fbf6d,0xbf65bf80bf71bf7d,
0xbf31bf73bf46bf7b,0xbefcbf58bf18bf67,0xbf7cbf4abf75bf35,0xbf7fbf6abf80bf5c,0x3f6f3f273f623f0e,0x3f7e3f513f783f3e,0x3e60be893dc9bec4,0x3ee6bcc93eacbe16,
0x3d493f183e483f35,0xbe793eacbdc93ef1,0xbf67bf04bf55bec4,0xbf7dbf3ebf75bf22,0x3f2c3e163f0e0000,0x3f5c3edb3f463e95,0x3f713f783f7b3f6d,0x3f4e3f803f623f7f,
0xbf80bf4ebf7bbf35,0xbf78bf71bf7fbf62,0xbedbbf5cbf0ebf6d,0xbe16bf2cbe95bf46,0x3f3e3f7d3f553f80,0x3f043f673f223f75,0xbeac3e79be483ec4,0xbf18bd49bef13dc9,
0x3efc3f6f3f223f7b,0x3e2f3f423eac3f5c,0x3f733f093f623ec4,0x3f803f4a3f7d3f2c,0xbdfbbf39be95bf55,0x3e60bee63d49bf18,0xbf7fbf51bf7fbf35,0xbf6abf77bf78bf67,
0xbf5fbeb8bf46be48,0xbf7cbf27bf71bf04,0x3ea13f583ef13f6d,0xbcc93f1d3e163f3e,0x3f7e3f313f753f0e,0x3f7a3f653f803f4e,0x3d97bf13bdc9bf35,0x3ecfbe893e79bedb,
0x3f0e3f7b3f353f80,0x3e483f553ec43f6d,0xbf55be48bf350000,0xbf7bbf0ebf6dbec4,0xbf0ebf7bbf35bf80,0xbe48bf55bec4bf6d,0x3f553e483f350000,0x3f7b3f0e3f6d3ec4,
0xbf55be48bf358000,0xbf7bbf0ebf6dbec4,0xbf0ebf7bbf35bf80,0xbe48bf55bec4bf6d,0x3f553e483f358000,0x3f7b3f0e3f6d3ec4,0x3f0e3f7b3f353f80,0x3e483f553ec43f6d,
0x3f5f3f6f3f753f55,0x3f133f7f3f3e3f7d,0x3ea1bf093dc9bf35,0x3f31bdfb3f04beac,0xbf1dbf80bf46bf7b,0xbe60bf65bedbbf78,0xbf273e2fbef13ec4,0xbf6abe89bf4ebd49,
0xbefc3eb8be953f0e,0xbf51bd97bf2c3e16,0x3f733f583f7f3f35,0x3f393f7e3f5c3f71,0x3f4a3cc93f22be48,0x3f7a3ee63f673e79,0xbf42bf7cbf62bf6d,0xbecfbf77bf18bf80,
0x3f673f5c3f7b3f35,0x3f183f803f463f75,0xbf3e3e16bf0e3ec4,0xbf78beacbf62bdc9,0xbf71be79bf550000,0xbf7dbf2cbf7fbef1,0x3d49bf4ebe48bf6d,0x3f04bedb3e95bf22,
0xbedb3f04be483f35,0xbf4e3d49bf223e95,0xbf2cbf7dbf55bf6d,0xbe79bf71bef1bf7f,0xbeacbf78bf0ebf80,0x3e16bf3ebdc9bf62,0x3f803f183f7b3ec4,0x3f5c3f673f753f46,
0x3f393f733f623f55,0x3e893f7a3f043f80,0x3e2fbf4abdc9bf6d,0x3f27beb83edbbf18,0xbf6abd97bf463e48,0xbf7ebf13bf7dbeac,0x3f583f5f3f753f35,0x3ee63f803f2c3f78,
0xbf313ea1bef13f0e,0xbf77be60bf5c3d49,0x3f7c3f1d3f7f3ec4,0x3f423f6f3f673f4e,0xbecfbf7fbf22bf7b,0x3dfbbf51be16bf71,0xbf093efcbe953f35,0xbf65bcc9bf3e3e79,
0xbdc9bf75bec4bf80,0x3ef1bf223e48bf55,0x3f463f623f6d3f35,0x3e953f7f3f0e3f7b,0xbf7fbe95bf6d0000,0xbf62bf46bf7bbf0e,0x3f22bef13ec4bf35,0x3f753dc93f55be48,
0x3f7f3e953f6d8000,0x3f623f463f7b3f0e,0xbf223ef1bec43f35,0xbf75bdc9bf553e48,0xbdc9bf75bec4bf80,0x3ef1bf223e48bf55,0x3f463f623f6d3f35,0x3e953f7f3f0e3f7b,
0x3e60bf5fbdc9bf7b,0x3f42becf3f04bf2c,0xbf393ee6bef13f35,0xbf7ebe2fbf673e16,0xbf51bf4abf75bf0e,0xbea1bf80bf18bf71,0x3eb83f7f3f223f6d,0xbe893f583d493f78,
0x3f7a3efc3f7f3e48,0x3f273f6a3f5c3f3e,0xbf31bf65bf62bf35,0xbdfbbf7cbedbbf7d,0x3f13bf1d3e95bf55,0x3f73bcc93f4ebeac,0xbf6f3d97bf463ec4,0xbf77bf09bf80be79,
0x3f4ebedb3f0ebf35,0x3f803e793f75bdc9,0xbf043f3ebe483f6d,0xbf713e16bf463ef1,0x3f7d3eac3f7b0000,0x3f2c3f5c3f623f22,0xbf783d49bf553ec4,0xbf67bf18bf7fbe95,
0x3f183f673f553f35,0xbd493f783e953f7f,0xbf5cbf2cbf7bbec4,0xbeacbf7dbf22bf62,0xbe163f713e483f80,0xbf3e3f04bef13f46,0xbe79bf80bf0ebf6d,0x3edbbf4e3dc9bf75,
0x3f653f093f7f3e48,0x3eb83f773f2c3f4e,0xbf4abf31bf75bec4,0xbe2fbf7fbf04bf67,0x3f273f513f623f0e,0xbcc93f7e3eac3f78,0xbefcbf6abf46bf35,0x3e60bf73be16bf80,
0xbee63f58bdc93f7b,0xbf6f3e89bf3e3f18,0x3f1dbf393e95bf6d,0x3f7cbd973f5cbedb,0xbf423f13bef13f55,0xbf80bdfbbf713e79,0x3f5fbecf3f22bf35,0x3f7a3ea13f7dbd49,
0xbec43f6d00003f80,0xbf6d3ec4bf353f35,0x3ec4bf6d0000bf80,0x3f6dbec43f35bf35,0xbec43f6d00003f80,0xbf6d3ec4bf353f35,0x3ec4bf6d0000bf80,0x3f6dbec43f35bf35,
0xbf6dbec4bf808000,0xbec4bf6dbf35bf35,0x3f6d3ec43f808000,0x3ec43f6d3f353f35,0xbf6dbec4bf808000,0xbec4bf6dbf35bf35,0x3f6d3ec43f808000,0x3ec43f6d3f353f35,
0xbf7f3e2fbf623f0e,0xbf39bf1dbf71be79,0x3f77beb83f46bf35,0x3f583ee63f7d3d49,0xbf73be60bf7f3e48,0xbecfbf5fbf3ebf18,0x3f7e3cc93f75bec4,0x3f133f423f5c3edb,
0xbd97bf7cbef1bf55,0x3f31bf4a3eacbf78,0x3e893f6f3f223f35,0xbf093f65be163f80,0x3ea1bf7abdc9bf7b,0x3f6abefc3f2cbf4e,0xbdfb3f803e953f6d,0xbf513f27bf043f67,
0xbe16bf71bf0ebf35,0x3f2cbf5c3e95bf7f,0xbe793f803e483f6d,0xbf673f18bf223f62,0xbf4ebedbbf7b0000,0xbd49bf78bef1bf46,0x3f043f3e3f553ec4,0xbeac3f7d3dc93f75,
0x3f7dbeac3f55bf35,0x3f3e3f043f753dc9,0xbf78bd49bf7b3ec4,0xbedbbf4ebf46bef1,0x3f18bf673e48bf80,0x3f80be793f62bf22,0xbf5c3f2cbf0e3f6d,0xbf71be16bf7f3e95,
0x3f7cbdfb3f75bf0e,0x3ee63f393f4e3eac,0xbf6a3f27bf223f6d,0xbf5fbe60bf803e79,0x3f09bf773dc9bf7b,0x3f7fbeb83f5cbf3e,0x3cc93f733ef13f35,0xbf4a3f51bedb3f7d,
0xbe2f3f7e3e953f55,0xbf653f31bf183f71,0xbecfbf42bf46bec4,0x3efcbf7a3d49bf78,0x3f583e893f7fbe48,0x3d973f6f3f043f2c,0xbf803ea1bf623f35,0xbf1dbf13bf67be16,
0x3f46bf623ec4bf80,0x3f75bdc93f7bbf0e,0xbf7f3e95bf6d3f35,0xbef1bf22bf55be48,0x3f223ef13f6d0000,0xbe953f7f3e483f55,0x3dc9bf75bec4bf35,0x3f62bf463f0ebf7b,
0x3f223ef13f6d8000,0xbe953f7f3e483f55,0x3dc9bf75bec4bf35,0x3f62bf463f0ebf7b,0xbf463f62bec43f80,0xbf753dc9bf7b3f0e,0x3f7fbe953f6dbf35,0x3ef13f223f553e48,
0x3eb83f273f463e48,0xbf1d3f7cbe163f71,0xbf7a3e89bf753f35,0xbea1bf31bf3ebe79,0xbf803ee6bf623f55,0xbefcbf09bf5cbd49,0x3f13bf7e3dc9bf6d,0x3f7fbecf3f67bf4e,
0xbf6f3f42bf223f7b,0xbf4abe2fbf7d3eac,0x3e60bf77be95bf35,0x3f73bf393f2cbf78,0x3cc9bf65bef1bf0e,0x3f5fbf583f04bf80,0x3f513dfb3f7fbec4,0xbd973f6a3edb3f18,
0xbf713e79bf7b3f35,0xbe16bf3ebf22be95,0x3d493f4e3f0e3ec4,0xbf5c3f67bef13f7f,0x3edb3f043f550000,0xbf183f80bdc93f62,0x3f2cbf7d3e48bf6d,0x3f78beac3f75bf46,
0x3eacbf78be48bf35,0x3f7dbf2c3f46bf75,0xbf803f18bf553f6d,0xbf04bedbbf623dc9,0xbf673f5cbf0e3f80,0xbf4ebd49bf7f3ef1,0x3f3e3e163f7bbec4,0xbe793f713e953f22,
0x3f7ebf393f46bf7b,0x3f093ea13f67be79,0xbd973f513ef13ec4,0xbf6f3f5fbf183f80,0xbf773ecfbf753f55,0xbe2fbf27bf2cbe16,0x3ee6bf7abdc9bf35,0x3f80bf1d3f5cbf71,
0x3dfb3f313f223e48,0xbf583f73bedb3f78,0xbf7f3f13bf623f6d,0xbeb8befcbf4e3d49,0x3e89bf6abe95bf0e,0x3f7cbf423f3ebf7d,0x3f65be603f7fbf35,0xbcc93f4a3f043eac,
0xbf7b3f55bf353f80,0xbf0ebe48bf6d3ec4,0x3e483f0e3f350000,0xbf553f7bbec43f6d,0x3f7bbf553f35bf80,0x3f0e3e483f6dbec4,0xbe48bf0ebf350000,0x3f55bf7b3ec4bf6d,
0xbe48bf0ebf358000,0x3f55bf7b3ec4bf6d,0xbf7b3f55bf353f80,0xbf0ebe48bf6d3ec4,0x3e483f0e3f358000,0xbf553f7bbec43f6d,0x3f7bbf553f35bf80,0x3f0e3e483f6dbec4,
0x3f4abf803e95bf55,0x3f58bea13f80bf4e,0x3f42be2f3f7fbf35,0xbeb83f5f3e793edb,0xbf773f6abf223f7b,0xbf13bd97bf713f04,0xbee6be60bf623ec4,0x3f31bf7e3e16bf3e,
0x3f1d3cc93f75bf0e,0xbf093f733d493f18,0xbf273f7cbdc93f35,0xbf6f3efcbf783f67,0xbe89becfbf463e48,0x3f51bf7f3eacbf5c,0x3f65bf7a3ef1bf6d,0x3f39bdfb3f7dbf2c,
0xbf3e3f7dbe483f35,0xbf5c3edbbf7f3f62,0x3eac3e793f55bec4,0xbf4e3f80be953f46,0x3d49bf18bf0e0000,0x3f78bf713f22bf75,0xbf673f04bf7b3f6d,0x3e16bf2cbef1bdc9,
0xbf2c3e16bf7b3f35,0x3f04bf67bdc9bef1,0xbf713f78bf0e3f6d,0xbf183d49bf753f22,0x3f80bf4e3f55bf80,0x3e793eac3f46be95,0x3edbbf5cbe48bec4,0x3f7dbf3e3f62bf7f,
0x3f6abf7f3ef1bf55,0x3f1dbe2f3f78bf3e,0x3f58befc3f7fbf6d,0xbea13f393eac3e16,0x3cc93ee63f22be48,0xbf773f7abf183f67,0xbf513f7ebe953f35,0xbf423eb8bf803f5c,
0x3ecf3d973f62bf0e,0xbf4a3f7cbe793f2c,0xbf093f5f3dc93ec4,0xbf733f31bf713f7d,0xbf803f65bf463f7b,0xbe89be60bf4e3edb,0xbf133dfbbf753f35,0x3f27bf6f3d49bf04,
0x3f75bf463f6dbf80,0xbdc93ef13f0ebe48,0x3f62bf7f3ec4bf35,0x3f22be953f7bbf55,0x3e95bf22bec40000,0x3f7fbf623f55bf7b,0xbef13dc9bf6d3f35,0x3f46bf753e48bf0e,
0xbe953f223ec48000,0xbf7f3f62bf553f7b,0x3ef1bdc93f6dbf35,0xbf463f75be483f0e,0x3f75bf463f6dbf80,0xbdc93ef13f0ebe48,0x3f62bf7f3ec4bf35,0x3f22be953f7bbf55,
0xbf513f1dbf7f3f7b,0x3ee6bf31be79bd49,0xbeb83d97bf623f35,0x3f5fbf7a3eacbf18,0xbf583f77be953f0e,0xbf273ecfbf7d3f67,0xbf803f73bf463f6d,0xbdfbbe2fbf3e3f04,
0x3f13bf4abdc9be48,0x3f65bf393f78bf80,0x3f6fbf7f3ef1bf35,0x3efcbe603f71bf4e,0xbf093e89bf753f55,0x3f42bf6a3e16bedb,0x3cc9bea1bf223ec4,0x3f7ebf7c3f2cbf5c,
0x3e79bd493f55bf35,0xbf713f7dbef13f22,0x3f18bedb3f7bbf6d,0xbf3e3f5cbdc93e95,0xbf043f2c3e480000,0xbf673f4ebf753f7f,0xbe163eac3f0ebec4,0xbf803f78bf463f62,
0xbf783f80bf0e3f35,0xbeac3e16bf623f46,0xbf4e3f67be483ec4,0xbf2c3f04bf7f3f75,0xbf5c3f3ebf7b3f80,0x3edbbf18be953dc9,0xbf7d3f71bf553f6d,0x3d49be79bf223ef1,
0x3f42bf513dc9be48,0x3f31bf1d3f80bf7d,0x3f5fbf6a3e95bec4,0x3f09bee63f78bf71,0x3f73bf7a3ef1bf0e,0x3eb8be893f67bf5c,0x3f7ebf803f22bf35,0x3e2fbd973f4ebf3e,
0x3f27bf133f7fbf7b,0xbf393f4abd493e16,0x3efcbecf3f75bf6d,0xbf583f65be793eac,0x3ea1be603f62bf55,0xbf6f3f77bedb3f04,0x3dfbbcc93f46bf35,0xbf7c3f7fbf183f2c,
0x3f003f003f003f00,0x3f003f003f003f00,0x3f003f003f003f00,0x3f003f003f003f00,0x3f003f003f003f00,0x3f003f003f003f00,0x3f003f003f003f00,0x3f003f003f003f00,
0xbf00bf003f003f00,0xbf00bf003f003f00,0xbf00bf003f003f00,0xbf00bf003f003f00,0xbf00bf003f003f00,0xbf00bf003f003f00,0xbf00bf003f003f00,0xbf00bf003f003f00,
0x3ea13e603e953e48,0x3eb83e893eac3e79,0x3dfb3cc93dc90000,0x3e2f3d973e163d49,0x3f273f133f223f0e,0x3f313f1d3f2c3f18,0x3efc3ecf3ef13ec4,0x3f093ee63f043edb,
0x3f733f7a3f753f7b,0x3f6f3f773f713f78,0x3f7e3f803f7f3f80,0x3f7c3f7f3f7d3f80,0x3f423f513f463f55,0x3f393f4a3f3e3f4e,0x3f5f3f6a3f623f6d,0x3f583f653f5c3f67,
0xbf04bf2cbf0ebf35,0xbedbbf18bef1bf22,0xbe16beacbe48bec4,0xbd49be79bdc9be95,0xbf78bf80bf7bbf80,0xbf71bf7dbf75bf7f,0xbf4ebf67bf55bf6d,0xbf3ebf5cbf46bf62,
0x3f5c3f3e3f553f35,0x3f673f4e3f623f46,0x3f7d3f713f7b3f6d,0x3f803f783f7f3f75,0x3e793d493e488000,0x3eac3e163e953dc9,0x3f183edb3f0e3ec4,0x3f2c3f043f223ef1,
0xbf58bf77bf62bf7b,0xbf42bf6abf4ebf71,0xbf80bf73bf7fbf6d,0xbf7ebf7cbf80bf78,0xbf51bf1dbf46bf0e,0xbf65bf39bf5cbf2c,0xbeb8bd97be950000,0xbefcbe60bedbbe16,
0x3f093e893ef13e48,0x3f273ecf3f183eac,0xbcc9bea1bdc9bec4,0x3dfbbe2f3d49be79,0xbf13bf4abf22bf55,0xbee6bf31bf04bf3e,0xbf6fbf7fbf75bf80,0xbf5fbf7abf67bf7d,
0x3f623f7f3f6d3f80,0x3f463f753f553f7b,0x3e953f223ec43f35,0x3dc93ef13e483f0e,0xbef1bdc9bec40000,0xbf22be95bf0ebe48,0xbf75bf46bf6dbf35,0xbf7fbf62bf7bbf55,
0xbef1bdc9bec48000,0xbf22be95bf0ebe48,0xbf75bf46bf6dbf35,0xbf7fbf62bf7bbf55,0xbf62bf7fbf6dbf80,0xbf46bf75bf55bf7b,0xbe95bf22bec4bf35,0xbdc9bef1be48bf0e,
0x3f803f653f7f3f55,0x3f773f7a3f7d3f71,0x3f133dfb3ef10000,0x3f423eb83f2c3e79,0xbecf3d97be953e48,0xbf1dbe2fbf04bd49,0x3f093f5f3f223f6d,0x3ea13f393edb3f4e,
0xbcc93ee63dc93f0e,0xbe893e60be163eac,0x3f513f7e3f623f80,0x3f273f6f3f3e3f78,0xbf6abf7fbf75bf7b,0xbf4abf7cbf5cbf80,0xbf58befcbf46bec4,0xbf73bf31bf67bf18,
0x3f803f4e3f7b3f35,0x3f783f713f7f3f62,0x3edb3f5c3f0e3f6d,0x3e163f2c3e953f46,0xbf3ebf7dbf55bf80,0xbf04bf67bf22bf75,0x3eacbe793e48bec4,0x3f183d493ef1bdc9,
0x3d493f183e483f35,0xbe793eacbdc93ef1,0xbf67bf04bf55bec4,0xbf7dbf3ebf75bf22,0x3f2c3e163f0e8000,0x3f5c3edb3f463e95,0x3f713f783f7b3f6d,0x3f4e3f803f623f7f,
0x3f773f6a3f7f3f55,0x3f513f7f3f673f78,0x3ee6be603e95bec4,0x3f393dfb3f18bd49,0xbf4abf80bf62bf7b,0xbf09bf73bf2cbf7d,0xbf42be2fbf220000,0xbf6fbefcbf5cbeac,
0xbe893ecfbdc93f0e,0xbf133d97bedb3e79,0x3f653f7a3f753f6d,0x3f313f7e3f4e3f80,0x3f1dbcc93ef1be48,0x3f583ea13f3e3e16,0xbf27bf7cbf46bf80,0xbeb8bf5fbf04bf71,
0x3f0e3f7b3f353f80,0x3e483f553ec43f6d,0xbf55be48bf350000,0xbf7bbf0ebf6dbec4,0xbf0ebf7bbf35bf80,0xbe48bf55bec4bf6d,0x3f553e483f350000,0x3f7b3f0e3f6d3ec4,
0xbf55be48bf358000,0xbf7bbf0ebf6dbec4,0xbf0ebf7bbf35bf80,0xbe48bf55bec4bf6d,0x3f553e483f358000,0x3f7b3f0e3f6d3ec4,0x3f0e3f7b3f353f80,0x3e483f553ec43f6d,
0x3e893f6a3ef13f7b,0xbe2f3f273d493f4e,0x3f653e603f460000,0x3f803f1d3f783edb,0x3dfbbf31bdc9bf55,0x3f09bea13eacbf04,0xbf7fbf13bf75bec4,0xbf6fbf5fbf7dbf3e,
0xbf77becfbf62be48,0xbf7cbf42bf80bf18,0x3ee63f7a3f223f80,0x3cc93f4a3e793f67,0x3f7e3f393f7f3f0e,0x3f583f733f713f5c,0xbd97bf51be95bf6d,0x3eb8befc3e16bf2c,
0xbedb3f04be483f35,0xbf4e3d49bf223e95,0xbf2cbf7dbf55bf6d,0xbe79bf71bef1bf7f,0xbeacbf78bf0ebf80,0x3e16bf3ebdc9bf62,0x3f803f183f7b3ec4,0x3f5c3f673f753f46,
0xbf67bf5cbf7bbf35,0xbf18bf80bf46bf75,0x3f3ebe163f0ebec4,0x3f783eac3f623dc9,0x3f713e793f558000,0x3f7d3f2c3f7f3ef1,0xbd493f4e3e483f6d,0xbf043edbbe953f22,
0xbf80bee6bf75be48,0xbf5fbf58bf78bf2c,0x3f133f7e3f463f6d,0x3d973f6a3eac3f7d,0x3eb8bf273dc9bf55,0x3f4abe2f3f18bedb,0xbf7abe89bf620000,0xbf73bf39bf80bf04,
0xbcc9bf65be95bf7b,0x3efcbf093e79bf3e,0xbf513dfbbf223ec4,0xbf7fbecfbf71be16,0x3f6f3f423f7f3f0e,0x3f1d3f7c3f4e3f67,0xbe60bf77bef1bf80,0x3ea1bf313d49bf5c,
0x3dc93f753ec43f80,0xbef13f22be483f55,0xbf46bf62bf6dbf35,0xbe95bf7fbf0ebf7b,0x3f7f3e953f6d0000,0x3f623f463f7b3f0e,0xbf223ef1bec43f35,0xbf75bdc9bf553e48,
0xbf7fbe95bf6d8000,0xbf62bf46bf7bbf0e,0x3f22bef13ec4bf35,0x3f753dc93f55be48,0x3dc93f753ec43f80,0xbef13f22be483f55,0xbf46bf62bf6dbf35,0xbe95bf7fbf0ebf7b,
0xbf583e89bf223f0e,0xbf7fbeb8bf78bd49,0x3f803ea13f750000,0x3f4a3f513f713f18,0x3e2f3f7e3ef13f7b,0xbee63f39be163f67,0x3ecfbf423dc9bf6d,0x3f5fbe603f2cbf04,
0xbf09bf77bf46bf55,0x3d97bf6fbe79bf80,0xbcc93f733e953f80,0xbf1d3f13beac3f4e,0xbf7cbdfbbf623e48,0xbf65bf31bf7dbedb,0x3f6a3f273f7f3ec4,0x3efc3f7a3f3e3f5c,
0xbf18bf67bf55bf35,0x3d49bf78be95bf7f,0x3f5c3f2c3f7b3ec4,0x3eac3f7d3f223f62,0x3e16bf71be48bf80,0x3f3ebf043ef1bf46,0x3e793f803f0e3f6d,0xbedb3f4ebdc93f75,
0x3f4ebedb3f0ebf35,0x3f803e793f75bdc9,0xbf043f3ebe483f6d,0xbf713e16bf463ef1,0x3f7d3eac3f7b8000,0x3f2c3f5c3f623f22,0xbf783d49bf553ec4,0xbf67bf18bf7fbe95,
0x3f73be603f46bf0e,0x3f6a3efc3f803e16,0xbf7e3cc9bf623ec4,0xbf51bf27bf78beac,0x3f7f3e2f3f75be48,0x3f313f4a3f673f04,0xbf77beb8bf7f0000,0xbf09bf65bf4ebf2c,
0x3ea13f7a3f223f55,0xbecf3f5fbd493f7d,0xbdfbbf80bef1bf6d,0x3f13bf423e79bf71,0xbd973f7c3e953f7b,0xbf393f1dbedb3f5c,0x3e89bf6fbdc9bf80,0x3f58bee63f18bf3e,
0xbec43f6d00003f80,0xbf6d3ec4bf353f35,0x3ec4bf6d0000bf80,0x3f6dbec43f35bf35,0xbec43f6d00003f80,0xbf6d3ec4bf353f35,0x3ec4bf6d0000bf80,0x3f6dbec43f35bf35,
0xbf6dbec4bf808000,0xbec4bf6dbf35bf35,0x3f6d3ec43f808000,0x3ec43f6d3f353f35,0xbf6dbec4bf808000,0xbec4bf6dbf35bf35,0x3f6d3ec43f808000,0x3ec43f6d3f353f35,
0xbf42bf13bf75be48,0xbcc9bf7ebedbbf5c,0x3f5f3ecf3f7f0000,0x3e603f733f183f3e,0xbee6bf58bf46bf0e,0x3eb8bf77bd49bf7d,0x3f1d3f393f623ec4,0xbe2f3f7f3e793f71,
0x3f27bf513e95bf7b,0x3f80bdfb3f67bf04,0xbefc3f6abdc93f80,0xbf7a3ea1bf4e3f2c,0x3f65bf093f22bf55,0x3f6f3e893f80be16,0xbf4a3f31bef13f6d,0xbf7cbd97bf783eac,
0x3f7dbeac3f55bf35,0x3f3e3f043f753dc9,0xbf78bd49bf7b3ec4,0xbedbbf4ebf46bef1,0x3f18bf673e48bf80,0x3f80be793f62bf22,0xbf5c3f2cbf0e3f6d,0xbf71be16bf7f3e95,
0x3e163f713f0e3f35,0xbf2c3f5cbe953f7f,0x3e79bf80be48bf6d,0x3f67bf183f22bf62,0x3f4e3edb3f7b8000,0x3d493f783ef13f46,0xbf04bf3ebf55bec4,0x3eacbf7dbdc9bf75,
0xbf513f4abef13f7b,0xbf73bcc9bf7d3edb,0x3eb8bf7fbdc9bf6d,0x3f77bf093f3ebf5c,0x3e603f5f3f223f0e,0xbf273f6abe793f80,0xbf39bee6bf750000,0x3dfbbf7cbeacbf4e,
0xbf13bf1dbf62be48,0x3ea1bf80be16bf67,0x3f6f3d973f7fbec4,0x3e893f583f2c3f04,0xbf7a3efcbf463f55,0xbf42becfbf783d49,0x3f31bf653e95bf80,0x3f7ebe2f3f71bf18,
0xbf463f62bec43f80,0xbf753dc9bf7b3f0e,0x3f7fbe953f6dbf35,0x3ef13f223f553e48,0xbf22bef1bf6d0000,0x3e95bf7fbe48bf55,0xbdc93f753ec43f35,0xbf623f46bf0e3f7b,
0xbf22bef1bf6d8000,0x3e95bf7fbe48bf55,0xbdc93f753ec43f35,0xbf623f46bf0e3f7b,0x3f46bf623ec4bf80,0x3f75bdc93f7bbf0e,0xbf7f3e95bf6d3f35,0xbef1bf22bf55be48,
0x3ecfbf7fbdc9bf55,0x3f7ebf133f4ebf67,0x3f093efc3f620000,0xbee63f803d493f5c,0x3f313ea13f75be48,0xbe893f7a3e793f3e,0xbf7c3f1dbf463f6d,0xbf27beb8bf713e16,
0x3f6abd973f7fbf0e,0x3dfb3f513f183edb,0xbf583f5fbef13f80,0xbf653cc9bf803f04,0xbf393f73be953f7b,0xbf773e60bf783f2c,0xbe2fbf4abf22bec4,0x3f42bf6f3eacbf7d,
0xbeac3f783e483f35,0xbf7d3f2cbf463f75,0x3f80bf183f55bf6d,0x3f043edb3f62bdc9,0x3f67bf5c3f0ebf80,0x3f4e3d493f7fbef1,0xbf3ebe16bf7b3ec4,0x3e79bf71be95bf22,
0xbf713e79bf7b3f35,0xbe16bf3ebf22be95,0x3d493f4e3f0e3ec4,0xbf5c3f67bef13f7f,0x3edb3f043f558000,0xbf183f80bdc93f62,0x3f2cbf7d3e48bf6d,0x3f78beac3f75bf46,
0x3f1dbf803dc9bf55,0x3f7abee63f71bf5c,0x3f273e2f3f75bec4,0xbecf3f773e163f2c,0xbf5f3f6fbef13f7b,0xbf513d97bf803f18,0xbea1bf09bf460000,0x3f39bf7e3e79bf67,
0x3f4abcc93f7fbf0e,0xbe603f653eac3f04,0xbf423f7cbe953f6d,0xbf6a3e89bf7d3f3e,0xbefcbeb8bf623e48,0x3f13bf7f3d49bf4e,0x3f73bf583f22bf80,0x3f313dfb3f78bedb,
0xbf7b3f55bf353f80,0xbf0ebe48bf6d3ec4,0x3e483f0e3f350000,0xbf553f7bbec43f6d,0x3f7bbf553f35bf80,0x3f0e3e483f6dbec4,0xbe48bf0ebf350000,0x3f55bf7b3ec4bf6d,
0xbe48bf0ebf358000,0x3f55bf7b3ec4bf6d,0xbf7b3f55bf353f80,0xbf0ebe48bf6d3ec4,0x3e483f0e3f358000,0xbf553f7bbec43f6d,0x3f7bbf553f35bf80,0x3f0e3e483f6dbec4,
0x3f7ebf313f62bf7b,0x3e603ee63f3ebe16,0x3d973f133f220000,0xbf6a3f77bf043f71,0xbf5f3eb8bf7f3f55,0x3e2fbf42bedbbe79,0x3ea1bf58be95bec4,0x3f80bf4a3f4ebf80,
0xbdfb3f393ef13e48,0xbf7a3f65bf2c3f7d,0xbf7f3f51bf463f80,0xbecfbe89bf5c3eac,0x3efcbf6fbdc9bf0e,0x3f7cbf273f67bf78,0x3f73bf093f75bf6d,0x3cc93f1d3f183d49,
0xbf2c3e16bf7b3f35,0x3f04bf67bdc9bef1,0xbf713f78bf0e3f6d,0xbf183d49bf753f22,0x3f80bf4e3f55bf80,0x3e793eac3f46be95,0x3edbbf5cbe48bec4,0x3f7dbf3e3f62bf7f,
0x3f3ebf7d3e48bf35,0x3f5cbedb3f7fbf62,0xbeacbe79bf553ec4,0x3f4ebf803e95bf46,0xbd493f183f0e8000,0xbf783f71bf223f75,0x3f67bf043f7bbf6d,0xbe163f2c3ef13dc9,
0xbeb83f423e953e48,0xbf7e3f51bf5c3f80,0xbf7a3f77bf223f6d,0xbee6bcc9bf673f18,0xbf393ea1bf7f3f55,0x3efcbf58be16beac,0x3e2fbf1dbef10000,0x3f7fbf6a3f3ebf78,
0xbf6f3f27bf753f7b,0x3dfbbf13bf043d49,0xbe60be89bf463ec4,0x3f65bf803edbbf4e,0x3f31bf733dc9bf0e,0x3f5fbf093f7dbf71,0x3f7cbf4a3f62bf80,0x3d973ecf3f2cbe79,
0xbf753f46bf6d3f80,0x3dc9bef1bf0e3e48,0xbf623f7fbec43f35,0xbf223e95bf7b3f55,0xbe953f223ec40000,0xbf7f3f62bf553f7b,0x3ef1bdc93f6dbf35,0xbf463f75be483f0e,
0x3e95bf22bec48000,0x3f7fbf623f55bf7b,0xbef13dc9bf6d3f35,0x3f46bf753e48bf0e,0xbf753f46bf6d3f80,0x3dc9bef1bf0e3e48,0xbf623f7fbec43f35,0xbf223e95bf7b3f55,
0x3e2f3dfb3f46bf0e,0xbf733f80bf043f3e,0xbecf3f273e950000,0xbf773f58bf673f7d,0x3f7abf5f3f62bf7b,0xbd973eb83f18beac,0x3f31bee63f7fbf6d,0xbf1d3f513d493e79,
0xbf7c3f7ebf223f55,0xbea13cc9bf5c3f2c,0xbf6a3f42bf753f80,0x3e89bf09bedb3e16,0xbe603efc3ef1be48,0xbf7f3f6fbf4e3f71,0xbf393f65bdc93ec4,0xbf4a3f13bf803f78,
0x3f78bf803f0ebf35,0x3eacbe163f62bf46,0x3f4ebf673e48bec4,0x3f2cbf043f7fbf75,0x3f5cbf3e3f7bbf80,0xbedb3f183e95bdc9,0x3f7dbf713f55bf6d,0xbd493e793f22bef1,
0x3e79bd493f55bf35,0xbf713f7dbef13f22,0x3f18bedb3f7bbf6d,0xbf3e3f5cbdc93e95,0xbf043f2c3e488000,0xbf673f4ebf753f7f,0xbe163eac3f0ebec4,0xbf803f78bf463f62,
0x3d97be2fbf223f0e,0x3f80bf7e3f3ebf4e,0x3e89beb8bef13ec4,0x3f7abf733f5cbf67,0x3ee6bf09be953e48,0x3f6abf5f3f71bf78,0x3f1dbf31bdc90000,0x3f51bf423f7dbf80,
0x3f7fbf7c3f46bf55,0xbcc93dfb3f2cbf18,0x3f77bf6f3f62bf6d,0xbe603ea13f04bedb,0x3f65bf583f75bf7b,0xbecf3efc3eacbe79,0x3f4abf393f7fbf80,0xbf133f273e16bd49,
0x3f003f003f003f00,0x3f003f003f003f00,0x3f003f003f003f00,0x3f003f003f003f00,0x3f003f003f003f00,0x3f003f003f003f00,0x3f003f003f003f00,0x3f003f003f003f00,
0xbf00bf003f003f00,0xbf00bf003f003f00,0xbf00bf003f003f00,0xbf00bf003f003f00,0xbf00bf003f003f00,0xbf00bf003f003f00,0xbf00bf003f003f00,0xbf00bf003f003f00,
0x3f653f583f623f55,0x3f6a3f5f3f673f5c,0x3f4a3f393f463f35,0x3f513f423f4e3f3e,0x3f7f3f7c3f7f3f7b,0x3f803f7e3f803f7d,0x3f773f6f3f753f6d,0x3f7a3f733f783f71,
0x3ee63f093ef13f0e,0x3ecf3efc3edb3f04,0x3f1d3f313f223f35,0x3f133f273f183f2c,0x3d973e2f3dc93e48,0x3cc93dfb3d493e16,0x3e893eb83e953ec4,0x3e603ea13e793eac,
0x3f5c3f3e3f553f35,0x3f673f4e3f623f46,0x3f7d3f713f7b3f6d,0x3f803f783f7f3f75,0x3e793d493e480000,0x3eac3e163e953dc9,0x3f183edb3f0e3ec4,0x3f2c3f043f223ef1,
0x3f043f2c3f0e3f35,0x3edb3f183ef13f22,0x3e163eac3e483ec4,0x3d493e793dc93e95,0x3f783f803f7b3f80,0x3f713f7d3f753f7f,0x3f4e3f673f553f6d,0x3f3e3f5c3f463f62,
0x3f7a3f5f3f753f55,0x3f7f3f6f3f7d3f67,0x3f313ee63f223ec4,0x3f4a3f133f3e3f04,0x3e2fbdfb3dc9be48,0x3ea13cc93e79bd49,0xbecfbf27bef1bf35,0xbe89bf09beacbf18,
0x3e603efc3e953f0e,0x3d973eb83e163edb,0x3f393f653f463f6d,0x3f1d3f513f2c3f5c,0x3f7c3f7e3f7f3f7b,0x3f733f803f783f80,0x3f6a3f423f623f35,0x3f773f583f713f4e,
0xbf62bf7fbf6dbf80,0xbf46bf75bf55bf7b,0xbe95bf22bec4bf35,0xbdc9bef1be48bf0e,0x3ef13dc93ec40000,0x3f223e953f0e3e48,0x3f753f463f6d3f35,0x3f7f3f623f7b3f55,
0x3ef13dc93ec48000,0x3f223e953f0e3e48,0x3f753f463f6d3f35,0x3f7f3f623f7b3f55,0x3f623f7f3f6d3f80,0x3f463f753f553f7b,0x3e953f223ec43f35,0x3dc93ef13e483f0e,
0xbf31bf73bf46bf7b,0xbefcbf58bf18bf67,0xbf7cbf4abf75bf35,0xbf7fbf6abf80bf5c,0x3f6f3f273f623f0e,0x3f7e3f513f783f3e,0x3e60be893dc9bec4,0x3ee6bcc93eacbe16,
0x3f393ea13f223e48,0x3f5f3f093f4e3edb,0xbe2fbf1dbe95bf35,0x3d97becfbd49bf04,0x3eb83f423ef13f55,0x3dfb3f133e793f2c,0x3f7a3f773f7f3f6d,0x3f653f803f713f7d,
0xbd49bf18be48bf35,0x3e79beac3dc9bef1,0x3f673f043f553ec4,0x3f7d3f3e3f753f22,0xbf2cbe16bf0e0000,0xbf5cbedbbf46be95,0xbf71bf78bf7bbf6d,0xbf4ebf80bf62bf7f,
0x3f803f4e3f7b3f35,0x3f783f713f7f3f62,0x3edb3f5c3f0e3f6d,0x3e163f2c3e953f46,0xbf3ebf7dbf55bf80,0xbf04bf67bf22bf75,0x3eacbe793e48bec4,0x3f183d493ef1bdc9,
0x3f5f3eb83f463e48,0x3f7c3f273f713f04,0xbea1bf58bef1bf6d,0x3cc9bf1dbe16bf3e,0xbf7ebf31bf75bf0e,0xbf7abf65bf80bf4e,0xbd973f133dc93f35,0xbecf3e89be793edb,
0x3efc3f6f3f223f7b,0x3e2f3f423eac3f5c,0x3f733f093f623ec4,0x3f803f4a3f7d3f2c,0xbdfbbf39be95bf55,0x3e60bee63d49bf18,0xbf7fbf51bf7fbf35,0xbf6abf77bf78bf67,
0x3f0e3f7b3f353f80,0x3e483f553ec43f6d,0xbf55be48bf350000,0xbf7bbf0ebf6dbec4,0xbf0ebf7bbf35bf80,0xbe48bf55bec4bf6d,0x3f553e483f350000,0x3f7b3f0e3f6d3ec4,
0xbf55be48bf358000,0xbf7bbf0ebf6dbec4,0xbf0ebf7bbf35bf80,0xbe48bf55bec4bf6d,0x3f553e483f358000,0x3f7b3f0e3f6d3ec4,0x3f0e3f7b3f353f80,0x3e483f553ec43f6d,
0xbefc3eb8be953f0e,0xbf51bd97bf2c3e16,0x3f733f583f7f3f35,0x3f393f7e3f5c3f71,0x3f4a3cc93f22be48,0x3f7a3ee63f673e79,0xbf42bf7cbf62bf6d,0xbecfbf77bf18bf80,
0xbf5fbf6fbf75bf55,0xbf13bf7fbf3ebf7d,0xbea13f09bdc93f35,0xbf313dfbbf043eac,0x3f1d3f803f463f7b,0x3e603f653edb3f78,0x3f27be2f3ef1bec4,0x3f6a3e893f4e3d49,
0xbf67bf5cbf7bbf35,0xbf18bf80bf46bf75,0x3f3ebe163f0ebec4,0x3f783eac3f623dc9,0x3f713e793f550000,0x3f7d3f2c3f7f3ef1,0xbd493f4e3e483f6d,0xbf043edbbe953f22,
0x3edbbf043e48bf35,0x3f4ebd493f22be95,0x3f2c3f7d3f553f6d,0x3e793f713ef13f7f,0x3eac3f783f0e3f80,0xbe163f3e3dc93f62,0xbf80bf18bf7bbec4,0xbf5cbf67bf75bf46,
0x3f31bea13ef1bf0e,0x3f773e603f5cbd49,0xbf7cbf1dbf7fbec4,0xbf42bf6fbf67bf4e,0x3ecf3f7f3f223f7b,0xbdfb3f513e163f71,0x3f09befc3e95bf35,0x3f653cc93f3ebe79,
0x3f393f733f623f55,0x3e893f7a3f043f80,0x3e2fbf4abdc9bf6d,0x3f27beb83edbbf18,0xbf6abd97bf463e48,0xbf7ebf13bf7dbeac,0x3f583f5f3f753f35,0x3ee63f803f2c3f78,
0xbdc9bf75bec4bf80,0x3ef1bf223e48bf55,0x3f463f623f6d3f35,0x3e953f7f3f0e3f7b,0xbf7fbe95bf6d0000,0xbf62bf46bf7bbf0e,0x3f22bef13ec4bf35,0x3f753dc93f55be48,
0x3f7f3e953f6d8000,0x3f623f463f7b3f0e,0xbf223ef1bec43f35,0xbf75bdc9bf553e48,0xbdc9bf75bec4bf80,0x3ef1bf223e48bf55,0x3f463f623f6d3f35,0x3e953f7f3f0e3f7b,
0x3f7a3efc3f7f3e48,0x3f273f6a3f5c3f3e,0xbf31bf65bf62bf35,0xbdfbbf7cbedbbf7d,0x3f13bf1d3e95bf55,0x3f73bcc93f4ebeac,0xbf6f3d97bf463ec4,0xbf77bf09bf80be79,
0xbe603f5f3dc93f7b,0xbf423ecfbf043f2c,0x3f39bee63ef1bf35,0x3f7e3e2f3f67be16,0x3f513f4a3f753f0e,0x3ea13f803f183f71,0xbeb8bf7fbf22bf6d,0x3e89bf58bd49bf78,
0xbf4e3edbbf0e3f35,0xbf80be79bf753dc9,0x3f04bf3e3e48bf6d,0x3f71be163f46bef1,0xbf7dbeacbf7b0000,0xbf2cbf5cbf62bf22,0x3f78bd493f55bec4,0x3f673f183f7f3e95,
0xbf18bf67bf55bf35,0x3d49bf78be95bf7f,0x3f5c3f2c3f7b3ec4,0x3eac3f7d3f223f62,0x3e16bf71be48bf80,0x3f3ebf043ef1bf46,0x3e793f803f0e3f6d,0xbedb3f4ebdc93f75,
0x3ee6bf583dc9bf7b,0x3f6fbe893f3ebf18,0xbf1d3f39be953f6d,0xbf7c3d97bf5c3edb,0x3f42bf133ef1bf55,0x3f803dfb3f71be79,0xbf5f3ecfbf223f35,0xbf7abea1bf7d3d49,
0x3f653f093f7f3e48,0x3eb83f773f2c3f4e,0xbf4abf31bf75bec4,0xbe2fbf7fbf04bf67,0x3f273f513f623f0e,0xbcc93f7e3eac3f78,0xbefcbf6abf46bf35,0x3e60bf73be16bf80,
0xbec43f6d00003f80,0xbf6d3ec4bf353f35,0x3ec4bf6d0000bf80,0x3f6dbec43f35bf35,0xbec43f6d00003f80,0xbf6d3ec4bf353f35,0x3ec4bf6d0000bf80,0x3f6dbec43f35bf35,
0xbf6dbec4bf808000,0xbec4bf6dbf35bf35,0x3f6d3ec43f808000,0x3ec43f6d3f353f35,0xbf6dbec4bf808000,0xbec4bf6dbf35bf35,0x3f6d3ec43f808000,0x3ec43f6d3f353f35,
0xbd97bf7cbef1bf55,0x3f31bf4a3eacbf78,0x3e893f6f3f223f35,0xbf093f65be163f80,0x3ea1bf7abdc9bf7b,0x3f6abefc3f2cbf4e,0xbdfb3f803e953f6d,0xbf513f27bf043f67,
0x3f7fbe2f3f62bf0e,0x3f393f1d3f713e79,0xbf773eb8bf463f35,0xbf58bee6bf7dbd49,0x3f733e603f7fbe48,0x3ecf3f5f3f3e3f18,0xbf7ebcc9bf753ec4,0xbf13bf42bf5cbedb,
0x3e163f713f0e3f35,0xbf2c3f5cbe953f7f,0x3e79bf80be48bf6d,0x3f67bf183f22bf62,0x3f4e3edb3f7b0000,0x3d493f783ef13f46,0xbf04bf3ebf55bec4,0x3eacbf7dbdc9bf75,
0xbf7d3eacbf553f35,0xbf3ebf04bf75bdc9,0x3f783d493f7bbec4,0x3edb3f4e3f463ef1,0xbf183f67be483f80,0xbf803e79bf623f22,0x3f5cbf2c3f0ebf6d,0x3f713e163f7fbe95,
0x3e2fbf7ebe95bf55,0x3f65bf313f18bf71,0x3ecf3f423f463ec4,0xbefc3f7abd493f78,0xbf58be89bf7f3e48,0xbd97bf6fbf04bf2c,0x3f80bea13f62bf35,0x3f1d3f133f673e16,
0x3f7cbdfb3f75bf0e,0x3ee63f393f4e3eac,0xbf6a3f27bf223f6d,0xbf5fbe60bf803e79,0x3f09bf773dc9bf7b,0x3f7fbeb83f5cbf3e,0x3cc93f733ef13f35,0xbf4a3f51bedb3f7d,
0x3f46bf623ec4bf80,0x3f75bdc93f7bbf0e,0xbf7f3e95bf6d3f35,0xbef1bf22bf55be48,0x3f223ef13f6d0000,0xbe953f7f3e483f55,0x3dc9bf75bec4bf35,0x3f62bf463f0ebf7b,
0x3f223ef13f6d8000,0xbe953f7f3e483f55,0x3dc9bf75bec4bf35,0x3f62bf463f0ebf7b,0xbf463f62bec43f80,0xbf753dc9bf7b3f0e,0x3f7fbe953f6dbf35,0x3ef13f223f553e48,
0xbf6f3f42bf223f7b,0xbf4abe2fbf7d3eac,0x3e60bf77be95bf35,0x3f73bf393f2cbf78,0x3cc9bf65bef1bf0e,0x3f5fbf583f04bf80,0x3f513dfb3f7fbec4,0xbd973f6a3edb3f18,
0xbeb8bf27bf46be48,0x3f1dbf7c3e16bf71,0x3f7abe893f75bf35,0x3ea13f313f3e3e79,0x3f80bee63f62bf55,0x3efc3f093f5c3d49,0xbf133f7ebdc93f6d,0xbf7f3ecfbf673f4e,
0x3f71be793f7bbf35,0x3e163f3e3f223e95,0xbd49bf4ebf0ebec4,0x3f5cbf673ef1bf7f,0xbedbbf04bf550000,0x3f18bf803dc9bf62,0xbf2c3f7dbe483f6d,0xbf783eacbf753f46,
0xbeac3f783e483f35,0xbf7d3f2cbf463f75,0x3f80bf183f55bf6d,0x3f043edb3f62bdc9,0x3f67bf5c3f0ebf80,0x3f4e3d493f7fbef1,0xbf3ebe16bf7b3ec4,0x3e79bf71be95bf22,
0xbdfbbf31bf22be48,0x3f58bf733edbbf78,0x3f7fbf133f62bf6d,0x3eb83efc3f4ebd49,0xbe893f6a3e953f0e,0xbf7c3f42bf3e3f7d,0xbf653e60bf7f3f35,0x3cc9bf4abf04beac,
0x3f7ebf393f46bf7b,0x3f093ea13f67be79,0xbd973f513ef13ec4,0xbf6f3f5fbf183f80,0xbf773ecfbf753f55,0xbe2fbf27bf2cbe16,0x3ee6bf7abdc9bf35,0x3f80bf1d3f5cbf71,
0xbf7b3f55bf353f80,0xbf0ebe48bf6d3ec4,0x3e483f0e3f350000,0xbf553f7bbec43f6d,0x3f7bbf553f35bf80,0x3f0e3e483f6dbec4,0xbe48bf0ebf350000,0x3f55bf7b3ec4bf6d,
0xbe48bf0ebf358000,0x3f55bf7b3ec4bf6d,0xbf7b3f55bf353f80,0xbf0ebe48bf6d3ec4,0x3e483f0e3f358000,0xbf553f7bbec43f6d,0x3f7bbf553f35bf80,0x3f0e3e483f6dbec4,
0x3f1d3cc93f75bf0e,0xbf093f733d493f18,0xbf273f7cbdc93f35,0xbf6f3efcbf783f67,0xbe89becfbf463e48,0x3f51bf7f3eacbf5c,0x3f65bf7a3ef1bf6d,0x3f39bdfb3f7dbf2c,
0xbf4a3f80be953f55,0xbf583ea1bf803f4e,0xbf423e2fbf7f3f35,0x3eb8bf5fbe79bedb,0x3f77bf6a3f22bf7b,0x3f133d973f71bf04,0x3ee63e603f62bec4,0xbf313f7ebe163f3e,
0x3f3ebf7d3e48bf35,0x3f5cbedb3f7fbf62,0xbeacbe79bf553ec4,0x3f4ebf803e95bf46,0xbd493f183f0e0000,0xbf783f71bf223f75,0x3f67bf043f7bbf6d,0xbe163f2c3ef13dc9,
0x3f2cbe163f7bbf35,0xbf043f673dc93ef1,0x3f71bf783f0ebf6d,0x3f18bd493f75bf22,0xbf803f4ebf553f80,0xbe79beacbf463e95,0xbedb3f5c3e483ec4,0xbf7d3f3ebf623f7f,
0xbecfbd97bf623f0e,0x3f4abf7c3e79bf2c,0x3f09bf5fbdc9bec4,0x3f73bf313f71bf7d,0x3f80bf653f46bf7b,0x3e893e603f4ebedb,0x3f13bdfb3f75bf35,0xbf273f6fbd493f04,
0x3f6abf7f3ef1bf55,0x3f1dbe2f3f78bf3e,0x3f58befc3f7fbf6d,0xbea13f393eac3e16,0x3cc93ee63f22be48,0xbf773f7abf183f67,0xbf513f7ebe953f35,0xbf423eb8bf803f5c,
0x3f75bf463f6dbf80,0xbdc93ef13f0ebe48,0x3f62bf7f3ec4bf35,0x3f22be953f7bbf55,0x3e95bf22bec40000,0x3f7fbf623f55bf7b,0xbef13dc9bf6d3f35,0x3f46bf753e48bf0e,
0xbe953f223ec48000,0xbf7f3f62bf553f7b,0x3ef1bdc93f6dbf35,0xbf463f75be483f0e,0x3f75bf463f6dbf80,0xbdc93ef13f0ebe48,0x3f62bf7f3ec4bf35,0x3f22be953f7bbf55,
0x3f13bf4abdc9be48,0x3f65bf393f78bf80,0x3f6fbf7f3ef1bf35,0x3efcbe603f71bf4e,0xbf093e89bf753f55,0x3f42bf6a3e16bedb,0x3cc9bea1bf223ec4,0x3f7ebf7c3f2cbf5c,
0x3f51bf1d3f7fbf7b,0xbee63f313e793d49,0x3eb8bd973f62bf35,0xbf5f3f7abeac3f18,0x3f58bf773e95bf0e,0x3f27becf3f7dbf67,0x3f80bf733f46bf6d,0x3dfb3e2f3f3ebf04,
0xbe793d49bf553f35,0x3f71bf7d3ef1bf22,0xbf183edbbf7b3f6d,0x3f3ebf5c3dc9be95,0x3f04bf2cbe480000,0x3f67bf4e3f75bf7f,0x3e16beacbf0e3ec4,0x3f80bf783f46bf62,
0x3f78bf803f0ebf35,0x3eacbe163f62bf46,0x3f4ebf673e48bec4,0x3f2cbf043f7fbf75,0x3f5cbf3e3f7bbf80,0xbedb3f183e95bdc9,0x3f7dbf713f55bf6d,0xbd493e793f22bef1,
0xbf273f13bf7f3f7b,0x3f39bf4a3d49be16,0xbefc3ecfbf753f6d,0x3f58bf653e79beac,0xbea13e60bf623f55,0x3f6fbf773edbbf04,0xbdfb3cc9bf463f35,0x3f7cbf7f3f18bf2c,
0x3f42bf513dc9be48,0x3f31bf1d3f80bf7d,0x3f5fbf6a3e95bec4,0x3f09bee63f78bf71,0x3f73bf7a3ef1bf0e,0x3eb8be893f67bf5c,0x3f7ebf803f22bf35,0x3e2fbd973f4ebf3e,
0x3f803f80,0xbf80bf80,0x3f803f80,0xbf80bf80,0x3f803f80,0xbf80bf80,0x3f803f80,0xbf80bf80,
0xbf80bf8080008000,0x3f803f8080008000,0xbf80bf8080008000,0x3f803f8080008000,0xbf80bf8080008000,0x3f803f8080008000,0xbf80bf8080008000,0x3f803f8080008000,
0xbea1be603f753f7b,0x3eb83e89bf71bf78,0xbdfbbcc93f7f3f80,0x3e2f3d97bf7dbf80,0xbf27bf133f463f55,0x3f313f1dbf3ebf4e,0xbefcbecf3f623f6d,0x3f093ee6bf5cbf67,
0xbf73bf7abe95be48,0x3f6f3f773eac3e79,0xbf7ebf80bdc98000,0x3f7c3f7f3e163d49,0xbf42bf51bf22bf0e,0x3f393f4a3f2c3f18,0xbf5fbf6abef1bec4,0x3f583f653f043edb,
0xbf5cbf3e3f0e3f35,0x3f673f4ebef1bf22,0xbf7dbf713e483ec4,0x3f803f78bdc9be95,0xbe79bd493f7b3f80,0x3eac3e16bf75bf7f,0xbf18bedb3f553f6d,0x3f2c3f04bf46bf62,
0xbf04bf2cbf55bf35,0x3edb3f183f623f46,0xbe16beacbf7bbf6d,0x3d493e793f7f3f75,0xbf78bf80be488000,0x3f713f7d3e953dc9,0xbf4ebf67bf0ebec4,0x3f3e3f5c3f223ef1,
0xbf58bf77bef1be48,0x3f423f6a3f183eac,0xbf80bf733dc93ec4,0x3f7e3f7c3d49be79,0xbf51bf1d3f223f55,0x3f653f39bf04bf3e,0xbeb8bd973f753f80,0x3efc3e60bf67bf7d,
0x3f093e89bf62bf7b,0xbf27becf3f4e3f71,0xbcc9bea1bf7fbf6d,0xbdfb3e2f3f803f78,0xbf13bf4abf46bf0e,0x3ee63f313f5c3f2c,0xbf6fbf7fbe958000,0x3f5f3f7a3edb3e16,
0xbef1bdc93f6d3f80,0x3f223e95bf55bf7b,0xbf75bf463ec43f35,0x3f7f3f62be48bf0e,0xbf62bf7fbec40000,0x3f463f753f0e3e48,0xbe95bf22bf6dbf35,0x3dc93ef13f7b3f55,
0xbf62bf7fbec48000,0x3f463f753f0e3e48,0xbe95bf22bf6dbf35,0x3dc93ef13f7b3f55,0x3ef13dc9bf6dbf80,0xbf22be953f553f7b,0x3f753f46bec4bf35,0xbf7fbf623e483f0e,
0xbf80bf653dc93f0e,0x3f773f7a3e16beac,0xbf13bdfb3f623f80,0x3f423eb8bf3ebf78,0x3ecfbd97bf75bf7b,0xbf1dbe2f3f5c3f80,0xbf09bf5fbf46bec4,0x3ea13f393f673f18,
0x3cc9bee6bf7fbf55,0xbe893e603f7d3f71,0xbf51bf7ebef18000,0x3f273f6f3f2c3e79,0x3f6a3f7f3e95be48,0xbf4abf7cbf04bd49,0x3f583efcbf22bf6d,0xbf73bf313edb3f4e,
0xbd49bf18bf7bbf35,0xbe793eac3f7f3f62,0x3f673f04bf0ebf6d,0xbf7dbf3e3e953f46,0xbf2cbe163f553f80,0x3f5c3edbbf22bf75,0xbf71bf78be483ec4,0x3f4e3f803ef1bdc9,
0x3f803f4ebe48bf35,0xbf78bf71bdc93ef1,0x3edb3f5c3f553ec4,0xbe16bf2cbf75bf22,0xbf3ebf7dbf0e8000,0x3f043f673f463e95,0x3eacbe79bf7bbf6d,0xbf18bd493f623f7f,
0x3f773f6a3dc9bf0e,0xbf51bf7fbedb3e79,0x3ee6be60bf75bf6d,0xbf39bdfb3f4e3f80,0xbf4abf80bef13e48,0x3f093f733f3e3e16,0xbf42be2f3f463f80,0x3f6f3efcbf04bf71,
0xbe893ecf3f7f3f55,0x3f13bd97bf67bf78,0x3f653f7a3e95bec4,0xbf31bf7ebf183d49,0x3f1dbcc9bf62bf7b,0xbf58bea13f2c3f7d,0xbf27bf7cbf228000,0x3eb83f5f3f5c3eac,
0xbf55be483f353f80,0x3f7b3f0ebec4bf6d,0xbf0ebf7bbf350000,0x3e483f553f6d3ec4,0x3f553e48bf35bf80,0xbf7bbf0e3ec43f6d,0x3f0e3f7b3f350000,0xbe48bf55bf6dbec4,
0xbf0ebf7bbf358000,0x3e483f553f6d3ec4,0x3f553e48bf35bf80,0xbf7bbf0e3ec43f6d,0x3f0e3f7b3f358000,0xbe48bf55bf6dbec4,0xbf55be483f353f80,0x3f7b3f0ebec4bf6d,
0xbe89bf6abf62be48,0xbe2f3f273f803f18,0xbf65be603f223f80,0x3f803f1dbe79bf67,0xbdfb3f313f7f3f0e,0x3f09bea1bf71bf5c,0x3f7f3f13be95bf6d,0xbf6fbf5fbe163f2c,
0x3f773ecfbef1bf7b,0xbf7cbf423d493f4e,0xbee6bf7abf468000,0x3cc93f4a3f783edb,0xbf7ebf393dc93f55,0x3f583f733eacbf04,0x3d973f513f753ec4,0x3eb8befcbf7dbf3e,
0x3f673f5c3e48bf35,0xbf18bf80bf223e95,0xbf3e3e163f553f6d,0x3f783eacbef1bf7f,0xbf71be793f0e3f80,0x3f7d3f2cbdc9bf62,0x3d49bf4ebf7bbec4,0xbf043edb3f753f46,
0xbedb3f043f7b3f35,0x3f4ebd49bf46bf75,0xbf2cbf7dbf0e3ec4,0x3e793f713f623dc9,0xbeacbf78bf558000,0xbe163f3e3f7f3ef1,0x3f803f18be48bf6d,0xbf5cbf67be953f22,
0xbf80bee63e953f7b,0x3f5f3f583e79bf3e,0x3f133f7e3f22bec4,0xbd97bf6abf71be16,0x3eb8bf27bf7fbf0e,0xbf4a3e2f3f4e3f67,0xbf7abe893ef13f80,0x3f733f393d49bf5c,
0xbcc9bf65bf75be48,0xbefc3f093f783f2c,0xbf513dfb3f463f6d,0x3f7f3ecfbeacbf7d,0x3f6f3f423dc9bf55,0xbf1dbf7cbf183edb,0xbe60bf77bf628000,0xbea13f313f803f04,
0xbf7fbe953ec43f80,0x3f623f463e48bf55,0x3f22bef1bf6dbf35,0xbf75bdc93f0e3f7b,0x3dc93f753f6d0000,0x3ef1bf22bf7bbf0e,0xbf46bf62bec43f35,0x3e953f7f3f55be48,
0xbdc9bf75bf6d8000,0xbef13f223f7b3f0e,0x3f463f623ec4bf35,0xbe95bf7fbf553e48,0xbf7fbe953ec43f80,0x3f623f463e48bf55,0x3f22bef1bf6dbf35,0xbf75bdc93f0e3f7b,
0x3f58be89bf46bf55,0xbf7fbeb83e793f80,0xbf80bea13e953f80,0x3f4a3f513eacbf4e,0xbe2fbf7ebf623e48,0xbee63f393f7d3edb,0xbecf3f423f7f3ec4,0x3f5fbe60bf3ebf5c,
0x3f093f773f22bf0e,0x3d97bf6fbf78bd49,0x3cc9bf73bf758000,0xbf1d3f133f713f18,0x3f7c3dfbbef1bf7b,0xbf65bf31be163f67,0xbf6abf27bdc93f6d,0x3efc3f7a3f2cbf04,
0xbf4e3edb3f553f35,0x3f803e79be95bf7f,0x3f04bf3ebf7bbec4,0xbf713e163f223f62,0xbf7dbeac3e483f80,0x3f2c3f5c3ef1bf46,0x3f78bd49bf0ebf6d,0xbf67bf18bdc93f75,
0xbf18bf67bf0e3f35,0xbd493f783f75bdc9,0x3f5c3f2c3e48bf6d,0xbeacbf7dbf463ef1,0x3e16bf71bf7b8000,0xbf3e3f043f623f22,0x3e793f803f55bec4,0x3edbbf4ebf7fbe95,
0x3f73be60bf22bf55,0xbf6abefcbd493f7d,0xbf7e3cc93ef13f6d,0x3f513f273e79bf71,0x3f7f3e2fbe95bf7b,0xbf31bf4abedb3f5c,0xbf77beb83dc93f80,0x3f093f653f18bf3e,
0x3ea13f7a3f46bf0e,0x3ecfbf5fbf80be16,0xbdfbbf80bf623ec4,0xbf133f423f783eac,0xbd973f7c3f75be48,0x3f39bf1dbf67bf04,0x3e89bf6fbf7f8000,0xbf583ee63f4e3f2c,
0xbf6dbec400003f80,0x3ec43f6d3f35bf35,0x3f6d3ec40000bf80,0xbec4bf6dbf353f35,0xbf6dbec400003f80,0x3ec43f6d3f35bf35,0x3f6d3ec40000bf80,0xbec4bf6dbf353f35,
0x3ec4bf6dbf808000,0xbf6d3ec43f353f35,0xbec43f6d3f808000,0x3f6dbec4bf35bf35,0x3ec4bf6dbf808000,0xbf6d3ec43f353f35,0xbec43f6d3f808000,0x3f6dbec4bf35bf35,
0x3f423f133e95bf7b,0xbcc9bf7ebf673f04,0xbf5fbecfbdc93f80,0x3e603f733f4ebf2c,0x3ee63f583f22bf55,0x3eb8bf77bf803e16,0xbf1dbf39bef13f6d,0xbe2f3f7f3f78beac,
0xbf273f513f753e48,0x3f80bdfbbedbbf5c,0x3efcbf6abf7f8000,0xbf7a3ea13f183f3e,0xbf653f093f463f0e,0x3f6f3e89bd49bf7d,0x3f4abf31bf62bec4,0xbf7cbd973e793f71,
0xbe16bf71bf553f35,0xbf2c3f5c3f753dc9,0xbe793f803f7bbec4,0x3f67bf18bf46bef1,0xbf4ebedbbe483f80,0x3d493f783f62bf22,0x3f043f3e3f0ebf6d,0x3eacbf7dbf7f3e95,
0x3f7dbeacbf0ebf35,0xbf3ebf04be953f7f,0xbf78bd493e483f6d,0x3edb3f4e3f22bf62,0x3f18bf67bf7b8000,0xbf803e793ef13f46,0xbf5c3f2c3f553ec4,0x3f713e16bdc9bf75,
0xbf513f4a3f623e48,0x3f733cc9be16bf67,0x3eb8bf7fbf7f3ec4,0xbf773f093f2c3f04,0x3e603f5f3f46bf55,0x3f27bf6abf783d49,0xbf39bee6be953f80,0xbdfb3f7c3f71bf18,
0xbf13bf1dbef13f7b,0xbea13f803f7dbedb,0x3f6f3d97bdc9bf6d,0xbe89bf58bf3e3f5c,0xbf7a3efc3f223f0e,0x3f423ecf3e79bf80,0x3f31bf65bf758000,0xbf7e3e2f3eac3f4e,
0xbf22bef1bec43f80,0xbe953f7f3f7bbf0e,0xbdc93f753f6dbf35,0x3f62bf46bf55be48,0x3f46bf62bf6d0000,0xbf753dc93e483f55,0xbf7f3e953ec43f35,0x3ef13f223f0ebf7b,
0x3f46bf62bf6d8000,0xbf753dc93e483f55,0xbf7f3e953ec43f35,0x3ef13f223f0ebf7b,0x3f223ef13ec4bf80,0x3e95bf7fbf7b3f0e,0x3dc9bf75bf6d3f35,0xbf623f463f553e48,
0xbecf3f7f3f7fbf0e,0x3f7ebf13bf18bedb,0xbf09befcbef13f80,0xbee63f803f80bf04,0xbf31bea1be953f7b,0xbe893f7a3f78bf2c,0x3f7cbf1dbf22bec4,0xbf27beb8beac3f7d,
0xbf6a3d973dc93f55,0x3dfb3f513f4ebf67,0x3f58bf5fbf628000,0xbf653cc93d493f5c,0x3f39bf73bf753e48,0xbf773e603e793f3e,0x3e2f3f4a3f46bf6d,0x3f42bf6fbf713e16,
0x3f71be79be48bf35,0xbe16bf3ebf463f75,0xbd49bf4ebf553f6d,0xbf5c3f673f62bdc9,0xbedbbf04bf0e3f80,0xbf183f803f7fbef1,0xbf2c3f7d3f7bbec4,0x3f78beacbe95bf22,
0xbeac3f783f7bbf35,0x3f7dbf2cbf22be95,0x3f80bf18bf0ebec4,0xbf04bedbbef13f7f,0x3f67bf5cbf558000,0xbf4ebd49bdc93f62,0xbf3ebe16be483f6d,0xbe793f713f75bf46,
0x3f1dbf80bf7f3f0e,0xbf7a3ee63eac3f04,0x3f273e2f3e95bf6d,0x3ecfbf77bf7d3f3e,0xbf5f3f6f3f62be48,0x3f51bd973d49bf4e,0xbea1bf09bf223f80,0xbf393f7e3f78bedb,
0x3f4abcc93dc9bf55,0x3e60bf65bf713f5c,0xbf423f7c3f75bec4,0x3f6abe89be16bf2c,0xbefcbeb8bef13f7b,0xbf133f7f3f80bf18,0x3f73bf58bf468000,0xbf31bdfbbe793f67,
0xbe48bf0ebf353f80,0xbf553f7b3f6dbec4,0xbf7b3f553f350000,0x3f0e3e483ec4bf6d,0x3e483f0e3f35bf80,0x3f55bf7bbf6d3ec4,0x3f7bbf55bf350000,0xbf0ebe48bec43f6d,
0x3f7bbf55bf358000,0xbf0ebe48bec43f6d,0xbe48bf0ebf353f80,0xbf553f7b3f6dbec4,0xbf7b3f553f358000,0x3f0e3e483ec4bf6d,0x3e483f0e3f35bf80,0x3f55bf7bbf6d3ec4,
0xbf7e3f313ef13e48,0x3e603ee63f2cbf7d,0xbd97bf13bf463f80,0xbf6a3f773f5cbeac,0x3f5fbeb8bdc9bf0e,0x3e2fbf42bf673f78,0xbea13f583f75bf6d,0x3f80bf4abf18bd49,
0x3dfbbf39bf623f7b,0xbf7a3f653f3ebe16,0x3f7fbf51bf228000,0xbecfbe89bf043f71,0xbefc3f6f3f7fbf55,0x3f7cbf27bedbbe79,0xbf733f093e953ec4,0x3cc93f1d3f4ebf80,
0xbf3e3f7d3f7bbf35,0x3f5cbedbbdc9bef1,0x3eac3e793f0ebf6d,0x3f4ebf80bf753f22,0x3d49bf18bf553f80,0xbf783f713f46be95,0xbf673f043e483ec4,0xbe163f2c3f62bf7f,
0xbf2c3e16be483f35,0xbf043f673f7fbf62,0xbf713f783f55bec4,0x3f18bd493e95bf46,0x3f80bf4ebf0e8000,0xbe79beacbf223f75,0x3edbbf5cbf7b3f6d,0xbf7d3f3e3ef13dc9,
0xbeb83f423f75bf7b,0x3f7ebf51bf043d49,0xbf7a3f773f46bec4,0x3ee63cc93edbbf4e,0xbf393ea1bdc93f0e,0xbefc3f583f7dbf71,0x3e2fbf1dbf623f80,0xbf7f3f6a3f2cbe79,
0xbf6f3f273e953e48,0xbdfb3f133f5cbf80,0xbe60be89bf223f6d,0xbf653f803f67bf18,0x3f31bf73bf7f3f55,0xbf5f3f093e163eac,0x3f7cbf4abef18000,0xbd97becfbf3e3f78,
0x3e95bf22bf6d3f80,0xbf7f3f623f0ebe48,0xbef13dc9bec43f35,0xbf463f753f7bbf55,0xbf753f463ec40000,0xbdc93ef13f55bf7b,0xbf623f7f3f6dbf35,0x3f22be953e48bf0e,
0x3f75bf46bec48000,0x3dc9bef1bf553f7b,0x3f62bf7fbf6d3f35,0xbf223e95be483f0e,0x3e95bf22bf6d3f80,0xbf7f3f623f0ebe48,0xbef13dc9bec43f35,0xbf463f753f7bbf55,
0xbe2fbdfbbf223f55,0xbf733f803f5cbf2c,0x3ecfbf27bf753f80,0xbf773f583edbbe16,0xbf7a3f5f3ef1be48,0xbd973eb83f4ebf71,0xbf313ee6bdc93ec4,0xbf1d3f513f80bf78,
0x3f7cbf7ebf463f0e,0xbea13cc9bf043f3e,0x3f6abf42be958000,0x3e89bf09bf673f7d,0x3e60befcbf623f7b,0xbf7f3f6f3f18beac,0x3f39bf65bf7f3f6d,0xbf4a3f133d493e79,
0xbe793d49bf0e3f35,0xbf713f7d3f62bf46,0xbf183edbbe483ec4,0xbf3e3f5c3f7fbf75,0x3f04bf2cbf7b3f80,0xbf673f4e3e95bdc9,0x3e16beacbf553f6d,0xbf803f783f22bef1,
0x3f78bf80bf553f35,0xbeac3e16bef13f22,0x3f4ebf67bf7b3f6d,0xbf2c3f04bdc93e95,0x3f5cbf3ebe488000,0x3edbbf18bf753f7f,0x3f7dbf71bf0e3ec4,0x3d49be79bf463f62,
0x3d97be2fbf463f55,0xbf803f7e3f2cbf18,0x3e89beb8bf623f6d,0xbf7a3f733f04bedb,0x3ee6bf09bf753f7b,0xbf6a3f5f3eacbe79,0x3f1dbf31bf7f3f80,0xbf513f423e16bd49,
0x3f7fbf7cbf223f0e,0x3cc9bdfbbf3e3f4e,0x3f77bf6fbef13ec4,0x3e60bea1bf5c3f67,0x3f65bf58be953e48,0x3ecfbefcbf713f78,0x3f4abf39bdc98000,0x3f13bf27bf7d3f80,
0x3f803f80,0xbf80bf80,0x3f803f80,0xbf80bf80,0x3f803f80,0xbf80bf80,0x3f803f80,0xbf80bf80,
0xbf80bf8080008000,0x3f803f8080008000,0xbf80bf8080008000,0x3f803f8080008000,0xbf80bf8080008000,0x3f803f8080008000,0xbf80bf8080008000,0x3f803f8080008000,
0xbf65bf583ef13f0e,0x3f6a3f5fbedbbf04,0xbf4abf393f223f35,0x3f513f42bf18bf2c,0xbf7fbf7c3dc93e48,0x3f803f7ebd49be16,0xbf77bf6f3e953ec4,0x3f7a3f73be79beac,
0xbee6bf09bf62bf55,0x3ecf3efc3f673f5c,0xbf1dbf31bf46bf35,0x3f133f273f4e3f3e,0xbd97be2fbf7fbf7b,0x3cc93dfb3f803f7d,0xbe89beb8bf75bf6d,0x3e603ea13f783f71,
0xbf04bf2cbf55bf35,0x3edb3f183f623f46,0xbe16beacbf7bbf6d,0x3d493e793f7f3f75,0xbf78bf80be480000,0x3f713f7d3e953dc9,0xbf4ebf67bf0ebec4,0x3f3e3f5c3f223ef1,
0x3f5c3f3ebf0ebf35,0xbf67bf4e3ef13f22,0x3f7d3f71be48bec4,0xbf80bf783dc93e95,0x3e793d49bf7bbf80,0xbeacbe163f753f7f,0x3f183edbbf55bf6d,0xbf2cbf043f463f62,
0x3f7a3f5fbe95bf0e,0xbf7fbf6f3e163edb,0x3f313ee6bf46bf6d,0xbf4abf133f2c3f5c,0x3e2fbdfbbf7fbf7b,0xbea1bcc93f783f80,0xbecfbf27bf62bf35,0x3e893f093f713f4e,
0x3e603efc3f753f55,0xbd97beb8bf7dbf67,0x3f393f653f223ec4,0xbf1dbf51bf3ebf04,0x3f7c3f7e3dc9be48,0xbf73bf80be793d49,0x3f6a3f42bef1bf35,0xbf77bf583eac3f18,
0x3ef13dc9bf6dbf80,0xbf22be953f553f7b,0x3f753f46bec4bf35,0xbf7fbf623e483f0e,0x3f623f7f3ec40000,0xbf46bf75bf0ebe48,0x3e953f223f6d3f35,0xbdc9bef1bf7bbf55,
0x3f623f7f3ec48000,0xbf46bf75bf0ebe48,0x3e953f223f6d3f35,0xbdc9bef1bf7bbf55,0xbef1bdc93f6d3f80,0x3f223e95bf55bf7b,0xbf75bf463ec43f35,0x3f7f3f62be48bf0e,
0x3f313f733f223e48,0xbefcbf58bf4ebedb,0x3f7c3f4abe95bf35,0xbf7fbf6a3d493f04,0xbf6fbf273ef13f55,0x3f7e3f51be79bf2c,0xbe603e893f7f3f6d,0x3ee6bcc9bf71bf7d,
0xbf39bea13f463f7b,0x3f5f3f09bf18bf67,0x3e2f3f1d3f753f35,0x3d97becfbf80bf5c,0xbeb8bf42bf62bf0e,0x3dfb3f133f783f3e,0xbf7abf77bdc93ec4,0x3f653f803eacbe16,
0xbf80bf4e3e483f35,0x3f783f713dc9bef1,0xbedbbf5cbf55bec4,0x3e163f2c3f753f22,0x3f3e3f7d3f0e0000,0xbf04bf67bf46be95,0xbeac3e793f7b3f6d,0x3f183d49bf62bf7f,
0xbd49bf18bf7bbf35,0xbe793eac3f7f3f62,0x3f673f04bf0ebf6d,0xbf7dbf3e3e953f46,0xbf2cbe163f553f80,0x3f5c3edbbf22bf75,0xbf71bf78be483ec4,0x3f4e3f803ef1bdc9,
0x3f5f3eb8bf22bf7b,0xbf7cbf273eac3f5c,0xbea1bf58bf62bec4,0xbcc93f1d3f7d3f2c,0xbf7ebf313e953f55,0x3f7a3f653d49bf18,0xbd973f133f7f3f35,0x3ecfbe89bf78bf67,
0x3efc3f6f3f463e48,0xbe2fbf42bf71bf04,0x3f733f09bef1bf6d,0xbf80bf4a3e163f3e,0xbdfbbf39bf75bf0e,0xbe603ee63f803f4e,0xbf7fbf513dc93f35,0x3f6a3f773e79bedb,
0xbf55be483f353f80,0x3f7b3f0ebec4bf6d,0xbf0ebf7bbf350000,0x3e483f553f6d3ec4,0x3f553e48bf35bf80,0xbf7bbf0e3ec43f6d,0x3f0e3f7b3f350000,0xbe48bf55bf6dbec4,
0xbf0ebf7bbf358000,0x3e483f553f6d3ec4,0x3f553e48bf35bf80,0xbf7bbf0e3ec43f6d,0x3f0e3f7b3f358000,0xbe48bf55bf6dbec4,0xbf55be483f353f80,0x3f7b3f0ebec4bf6d,
0x3efcbeb8bf75bf55,0xbf51bd973f3e3f7d,0xbf73bf58bdc93f35,0x3f393f7e3f04beac,0xbf4abcc93f463f7b,0x3f7a3ee6bedbbf78,0x3f423f7c3ef1bec4,0xbecfbf77bf4ebd49,
0x3f5f3f6f3e95bf0e,0xbf13bf7fbf2c3e16,0x3ea1bf09bf7fbf35,0xbf313dfb3f5c3f71,0xbf1dbf80bf223e48,0x3e603f653f673e79,0xbf273e2f3f623f6d,0x3f6a3e89bf18bf80,
0xbedb3f043f7b3f35,0x3f4ebd49bf46bf75,0xbf2cbf7dbf0e3ec4,0x3e793f713f623dc9,0xbeacbf78bf550000,0xbe163f3e3f7f3ef1,0x3f803f18be48bf6d,0xbf5cbf67be953f22,
0xbf67bf5cbe483f35,0x3f183f803f22be95,0x3f3ebe16bf55bf6d,0xbf78beac3ef13f7f,0x3f713e79bf0ebf80,0xbf7dbf2c3dc93f62,0xbd493f4e3f7b3ec4,0x3f04bedbbf75bf46,
0x3f31bea1bf62bf55,0xbf77be603f043f80,0xbf7cbf1d3dc93f6d,0x3f423f6f3edbbf18,0x3ecf3f7f3f46be48,0x3dfbbf51bf7dbeac,0x3f09befcbf75bf35,0xbf65bcc93f2c3f78,
0x3f393f733ef1bf0e,0xbe89bf7abf5c3d49,0x3e2fbf4abf7fbec4,0xbf273eb83f673f4e,0xbf6abd973f223f7b,0x3f7e3f13be16bf71,0x3f583f5f3e95bf35,0xbee6bf80bf3e3e79,
0x3f7f3e95bec4bf80,0xbf62bf46be483f55,0xbf223ef13f6d3f35,0x3f753dc9bf0ebf7b,0xbdc9bf75bf6d0000,0xbef13f223f7b3f0e,0x3f463f623ec4bf35,0xbe95bf7fbf553e48,
0x3dc93f753f6d8000,0x3ef1bf22bf7bbf0e,0xbf46bf62bec43f35,0x3e953f7f3f55be48,0x3f7f3e95bec4bf80,0xbf62bf46be483f55,0xbf223ef13f6d3f35,0x3f753dc9bf0ebf7b,
0xbf7abefc3dc93f7b,0x3f273f6a3f04bf2c,0x3f313f653ef1bf35,0xbdfbbf7cbf673e16,0xbf133f1d3f753f0e,0x3f73bcc9bf18bf71,0x3f6fbd97bf22bf6d,0xbf77bf093d493f78,
0x3e60bf5fbf7fbe48,0xbf423ecf3f5c3f3e,0xbf393ee63f623f35,0x3f7e3e2fbedbbf7d,0xbf51bf4abe953f55,0x3ea13f803f4ebeac,0x3eb83f7f3f46bec4,0x3e89bf58bf80be79,
0x3f183f673f0ebf35,0x3d49bf78bf753dc9,0xbf5cbf2cbe483f6d,0x3eac3f7d3f46bef1,0xbe163f713f7b0000,0x3f3ebf04bf62bf22,0xbe79bf80bf553ec4,0xbedb3f4e3f7f3e95,
0xbf4e3edb3f553f35,0x3f803e79be95bf7f,0x3f04bf3ebf7bbec4,0xbf713e163f223f62,0xbf7dbeac3e483f80,0x3f2c3f5c3ef1bf46,0x3f78bd49bf0ebf6d,0xbf67bf18bdc93f75,
0x3ee6bf58bf7fbe48,0xbf6f3e893f2c3f4e,0xbf1d3f393f753ec4,0x3f7cbd97bf04bf67,0x3f42bf13bf62bf0e,0xbf80bdfb3eac3f78,0xbf5f3ecf3f463f35,0x3f7a3ea1be16bf80,
0x3f653f093dc9bf7b,0xbeb8bf77bf3e3f18,0xbf4abf31be953f6d,0x3e2f3f7f3f5cbedb,0x3f273f513ef1bf55,0x3cc9bf7ebf713e79,0xbefcbf6abf223f35,0xbe603f733f7dbd49,
0xbf6dbec400003f80,0x3ec43f6d3f35bf35,0x3f6d3ec40000bf80,0xbec4bf6dbf353f35,0xbf6dbec400003f80,0x3ec43f6d3f35bf35,0x3f6d3ec40000bf80,0xbec4bf6dbf353f35,
0x3ec4bf6dbf808000,0xbf6d3ec43f353f35,0xbec43f6d3f808000,0x3f6dbec4bf35bf35,0x3ec4bf6dbf808000,0xbf6d3ec43f353f35,0xbec43f6d3f808000,0x3f6dbec4bf35bf35,
0x3d973f7c3f62bf0e,0x3f31bf4abf71be79,0xbe89bf6fbf463f35,0xbf093f653f7d3d49,0xbea13f7a3f7fbe48,0x3f6abefcbf3ebf18,0x3dfbbf80bf753ec4,0xbf513f273f5c3edb,
0xbf7f3e2f3ef13f55,0x3f393f1d3eacbf78,0x3f77beb8bf22bf35,0xbf58bee6be163f80,0xbf73be603dc93f7b,0x3ecf3f5f3f2cbf4e,0x3f7e3cc9be95bf6d,0xbf13bf42bf043f67,
0x3f7dbeacbf0ebf35,0xbf3ebf04be953f7f,0xbf78bd493e483f6d,0x3edb3f4e3f22bf62,0x3f18bf67bf7b0000,0xbf803e793ef13f46,0xbf5c3f2c3f553ec4,0x3f713e16bdc9bf75,
0x3e163f713f55bf35,0x3f2cbf5cbf75bdc9,0x3e79bf80bf7b3ec4,0xbf673f183f463ef1,0x3f4e3edb3e48bf80,0xbd49bf78bf623f22,0xbf04bf3ebf0e3f6d,0xbeac3f7d3f7fbe95,
0x3e2fbf7ebf753f0e,0xbf653f313f4e3eac,0x3ecf3f423f22bf6d,0x3efcbf7abf803e79,0xbf58be89bdc93f7b,0x3d973f6f3f5cbf3e,0x3f80bea1bef1bf35,0xbf1dbf13bedb3f7d,
0x3f7cbdfbbe95bf55,0xbee6bf39bf183f71,0xbf6a3f273f463ec4,0x3f5f3e603d49bf78,0x3f09bf77bf7f3e48,0xbf7f3eb83f043f2c,0x3cc93f733f62bf35,0x3f4abf51bf67be16,
0x3f223ef13ec4bf80,0x3e95bf7fbf7b3f0e,0x3dc9bf75bf6d3f35,0xbf623f463f553e48,0xbf463f623f6d0000,0x3f75bdc9be48bf55,0x3f7fbe95bec4bf35,0xbef1bf22bf0e3f7b,
0xbf463f623f6d8000,0x3f75bdc9be48bf55,0x3f7fbe95bec4bf35,0xbef1bf22bf0e3f7b,0xbf22bef1bec43f80,0xbe953f7f3f7bbf0e,0xbdc93f753f6dbf35,0x3f62bf46bf55be48,
0x3f6fbf42bf46be48,0xbf4abe2fbe163f71,0xbe603f773f75bf35,0x3f73bf39bf3ebe79,0xbcc93f653f62bf55,0x3f5fbf58bf5cbd49,0xbf51bdfbbdc93f6d,0xbd973f6a3f67bf4e,
0x3eb83f273f22bf7b,0x3f1dbf7cbf7d3eac,0xbf7a3e893e953f35,0x3ea13f313f2cbf78,0xbf803ee63ef13f0e,0x3efc3f093f04bf80,0x3f13bf7ebf7f3ec4,0xbf7f3ecf3edb3f18,
0x3eacbf78bf7b3f35,0xbf7d3f2c3f223e95,0xbf803f183f0e3ec4,0x3f043edb3ef1bf7f,0xbf673f5c3f550000,0x3f4e3d493dc9bf62,0x3f3e3e163e48bf6d,0x3e79bf71bf753f46,
0x3f71be79be48bf35,0xbe16bf3ebf463f75,0xbd49bf4ebf553f6d,0xbf5c3f673f62bdc9,0xbedbbf04bf0e3f80,0xbf183f803f7fbef1,0xbf2c3f7d3f7bbec4,0x3f78beacbe95bf22,
0xbdfbbf31bf463f7b,0xbf583f733f67be79,0x3f7fbf13bef1bec4,0xbeb8befcbf183f80,0xbe893f6a3f75bf55,0x3f7cbf42bf2cbe16,0xbf653e603dc93f35,0xbcc93f4a3f5cbf71,
0x3f7ebf39bf22be48,0xbf09bea1bedb3f78,0xbd973f513f62bf6d,0x3f6fbf5fbf4e3d49,0xbf773ecf3e953f0e,0x3e2f3f273f3ebf7d,0x3ee6bf7abf7f3f35,0xbf803f1d3f043eac,
0xbe48bf0ebf353f80,0xbf553f7b3f6dbec4,0xbf7b3f553f350000,0x3f0e3e483ec4bf6d,0x3e483f0e3f35bf80,0x3f55bf7bbf6d3ec4,0x3f7bbf55bf350000,0xbf0ebe48bec43f6d,
0x3f7bbf55bf358000,0xbf0ebe48bec43f6d,0xbe48bf0ebf353f80,0xbf553f7b3f6dbec4,0xbf7b3f553f358000,0x3f0e3e483ec4bf6d,0x3e483f0e3f35bf80,0x3f55bf7bbf6d3ec4,
0xbf1dbcc9be953f55,0xbf093f733f80bf4e,0x3f27bf7cbf7f3f35,0xbf6f3efc3e793edb,0x3e893ecf3f22bf7b,0x3f51bf7fbf713f04,0xbf653f7a3f62bec4,0x3f39bdfb3e16bf3e,
0x3f4abf80bf753f0e,0xbf583ea13d493f18,0x3f42be2f3dc9bf35,0x3eb8bf5fbf783f67,0xbf773f6a3f46be48,0x3f133d973eacbf5c,0xbee6be60bef13f6d,0xbf313f7e3f7dbf2c,
0xbf2c3e16be483f35,0xbf043f673f7fbf62,0xbf713f783f55bec4,0x3f18bd493e95bf46,0x3f80bf4ebf0e0000,0xbe79beacbf223f75,0x3edbbf5cbf7b3f6d,0xbf7d3f3e3ef13dc9,
0x3f3ebf7dbf7b3f35,0xbf5c3edb3dc93ef1,0xbeacbe79bf0e3f6d,0xbf4e3f803f75bf22,0xbd493f183f55bf80,0x3f78bf71bf463e95,0x3f67bf04be48bec4,0x3e16bf2cbf623f7f,
0xbecfbd97bef13f55,0xbf4a3f7c3f78bf3e,0x3f09bf5fbf7f3f6d,0xbf733f313eac3e16,0x3f80bf65bf223e48,0xbe89be60bf183f67,0x3f13bdfb3e95bf35,0x3f27bf6fbf803f5c,
0x3f6abf7fbf623f0e,0xbf1d3e2fbe793f2c,0x3f58befcbdc9bec4,0x3ea1bf39bf713f7d,0x3cc93ee63f46bf7b,0x3f77bf7abf4e3edb,0xbf513f7e3f75bf35,0x3f42beb83d49bf04,
0xbe953f223f6dbf80,0x3f7fbf62bf0e3e48,0x3ef1bdc93ec4bf35,0x3f46bf75bf7b3f55,0x3f75bf46bec40000,0x3dc9bef1bf553f7b,0x3f62bf7fbf6d3f35,0xbf223e95be483f0e,
0xbf753f463ec48000,0xbdc93ef13f55bf7b,0xbf623f7f3f6dbf35,0x3f22be953e48bf0e,0xbe953f223f6dbf80,0x3f7fbf62bf0e3e48,0x3ef1bdc93ec4bf35,0x3f46bf75bf7b3f55,
0xbf133f4a3f7fbf7b,0x3f65bf39be79bd49,0xbf6f3f7f3f62bf35,0x3efcbe603eacbf18,0x3f09be893e95bf0e,0x3f42bf6abf7d3f67,0xbcc93ea13f46bf6d,0x3f7ebf7cbf3e3f04,
0xbf513f1d3dc93e48,0xbee63f313f78bf80,0xbeb83d97bef13f35,0xbf5f3f7a3f71bf4e,0xbf583f773f75bf55,0x3f27becf3e16bedb,0xbf803f733f22bec4,0x3dfb3e2f3f2cbf5c,
0xbf783f803f55bf35,0x3eacbe163ef1bf22,0xbf4e3f673f7bbf6d,0x3f2cbf043dc9be95,0xbf5c3f3e3e480000,0xbedb3f183f75bf7f,0xbf7d3f713f0ebec4,0xbd493e793f46bf62,
0xbe793d49bf0e3f35,0xbf713f7d3f62bf46,0xbf183edbbe483ec4,0xbf3e3f5c3f7fbf75,0x3f04bf2cbf7b3f80,0xbf673f4e3e95bdc9,0x3e16beacbf553f6d,0xbf803f783f22bef1,
0xbf273f13bdc93e48,0xbf393f4a3f80bf7d,0xbefc3ecfbe953ec4,0xbf583f653f78bf71,0xbea13e60bef13f0e,0xbf6f3f773f67bf5c,0xbdfb3cc9bf223f35,0xbf7c3f7f3f4ebf3e,
0x3f42bf51bf7f3f7b,0xbf313f1dbd493e16,0x3f5fbf6abf753f6d,0xbf093ee6be793eac,0x3f73bf7abf623f55,0xbeb83e89bedb3f04,0x3f7ebf80bf463f35,0xbe2f3d97bf183f2c,
0x3f803f80,0xbf80bf80,0x3f803f80,0xbf80bf80,0x3f803f80,0xbf80bf80,0x3f803f80,0xbf80bf80,
0xbf80bf8080008000,0x3f803f8080008000,0xbf80bf8080008000,0x3f803f8080008000,0xbf80bf8080008000,0x3f803f8080008000,0xbf80bf8080008000,0x3f803f8080008000,
0xbf73bf7abe95be48,0x3f6f3f773eac3e79,0xbf7ebf80bdc90000,0x3f7c3f7f3e163d49,0xbf42bf51bf22bf0e,0x3f393f4a3f2c3f18,0xbf5fbf6abef1bec4,0x3f583f653f043edb,
0x3ea13e60bf75bf7b,0xbeb8be893f713f78,0x3dfb3cc9bf7fbf80,0xbe2fbd973f7d3f80,0x3f273f13bf46bf55,0xbf31bf1d3f3e3f4e,0x3efc3ecfbf62bf6d,0xbf09bee63f5c3f67,
0x3f5c3f3ebf0ebf35,0xbf67bf4e3ef13f22,0x3f7d3f71be48bec4,0xbf80bf783dc93e95,0x3e793d49bf7bbf80,0xbeacbe163f753f7f,0x3f183edbbf55bf6d,0xbf2cbf043f463f62,
0x3f043f2c3f553f35,0xbedbbf18bf62bf46,0x3e163eac3f7b3f6d,0xbd49be79bf7fbf75,0x3f783f803e488000,0xbf71bf7dbe95bdc9,0x3f4e3f673f0e3ec4,0xbf3ebf5cbf22bef1,
0xbf09be893f623f7b,0x3f273ecfbf4ebf71,0x3cc93ea13f7f3f6d,0x3dfbbe2fbf80bf78,0x3f133f4a3f463f0e,0xbee6bf31bf5cbf2c,0x3f6f3f7f3e950000,0xbf5fbf7abedbbe16,
0xbf58bf77bef1be48,0x3f423f6a3f183eac,0xbf80bf733dc93ec4,0x3f7e3f7c3d49be79,0xbf51bf1d3f223f55,0x3f653f39bf04bf3e,0xbeb8bd973f753f80,0x3efc3e60bf67bf7d,
0xbef1bdc93f6d3f80,0x3f223e95bf55bf7b,0xbf75bf463ec43f35,0x3f7f3f62be48bf0e,0xbf62bf7fbec40000,0x3f463f753f0e3e48,0xbe95bf22bf6dbf35,0x3dc93ef13f7b3f55,
0xbf62bf7fbec48000,0x3f463f753f0e3e48,0xbe95bf22bf6dbf35,0x3dc93ef13f7b3f55,0x3ef13dc9bf6dbf80,0xbf22be953f553f7b,0x3f753f46bec4bf35,0xbf7fbf623e483f0e,
0x3cc9bee6bf7fbf55,0xbe893e603f7d3f71,0xbf51bf7ebef10000,0x3f273f6f3f2c3e79,0x3f6a3f7f3e95be48,0xbf4abf7cbf04bd49,0x3f583efcbf22bf6d,0xbf73bf313edb3f4e,
0x3f803f65bdc9bf0e,0xbf77bf7abe163eac,0x3f133dfbbf62bf80,0xbf42beb83f3e3f78,0xbecf3d973f753f7b,0x3f1d3e2fbf5cbf80,0x3f093f5f3f463ec4,0xbea1bf39bf67bf18,
0x3d493f183f7b3f35,0x3e79beacbf7fbf62,0xbf67bf043f0e3f6d,0x3f7d3f3ebe95bf46,0x3f2c3e16bf55bf80,0xbf5cbedb3f223f75,0x3f713f783e48bec4,0xbf4ebf80bef13dc9,
0xbf80bf4e3e483f35,0x3f783f713dc9bef1,0xbedbbf5cbf55bec4,0x3e163f2c3f753f22,0x3f3e3f7d3f0e8000,0xbf04bf67bf46be95,0xbeac3e793f7b3f6d,0x3f183d49bf62bf7f,
0x3e89becfbf7fbf55,0xbf133d973f673f78,0xbf65bf7abe953ec4,0x3f313f7e3f18bd49,0xbf1d3cc93f623f7b,0x3f583ea1bf2cbf7d,0x3f273f7c3f220000,0xbeb8bf5fbf5cbeac,
0x3f773f6a3dc9bf0e,0xbf51bf7fbedb3e79,0x3ee6be60bf75bf6d,0xbf39bdfb3f4e3f80,0xbf4abf80bef13e48,0x3f093f733f3e3e16,0xbf42be2f3f463f80,0x3f6f3efcbf04bf71,
0xbf55be483f353f80,0x3f7b3f0ebec4bf6d,0xbf0ebf7bbf350000,0x3e483f553f6d3ec4,0x3f553e48bf35bf80,0xbf7bbf0e3ec43f6d,0x3f0e3f7b3f350000,0xbe48bf55bf6dbec4,
0xbf0ebf7bbf358000,0x3e483f553f6d3ec4,0x3f553e48bf35bf80,0xbf7bbf0e3ec43f6d,0x3f0e3f7b3f358000,0xbe48bf55bf6dbec4,0xbf55be483f353f80,0x3f7b3f0ebec4bf6d,
0x3f773ecfbef1bf7b,0xbf7cbf423d493f4e,0xbee6bf7abf460000,0x3cc93f4a3f783edb,0xbf7ebf393dc93f55,0x3f583f733eacbf04,0x3d973f513f753ec4,0x3eb8befcbf7dbf3e,
0x3e893f6a3f623e48,0x3e2fbf27bf80bf18,0x3f653e60bf22bf80,0xbf80bf1d3e793f67,0x3dfbbf31bf7fbf0e,0xbf093ea13f713f5c,0xbf7fbf133e953f6d,0x3f6f3f5f3e16bf2c,
0xbf67bf5cbe483f35,0x3f183f803f22be95,0x3f3ebe16bf55bf6d,0xbf78beac3ef13f7f,0x3f713e79bf0ebf80,0xbf7dbf2c3dc93f62,0xbd493f4e3f7b3ec4,0x3f04bedbbf75bf46,
0x3edbbf04bf7bbf35,0xbf4e3d493f463f75,0x3f2c3f7d3f0ebec4,0xbe79bf71bf62bdc9,0x3eac3f783f558000,0x3e16bf3ebf7fbef1,0xbf80bf183e483f6d,0x3f5c3f673e95bf22,
0x3cc93f653f753e48,0x3efcbf09bf78bf2c,0x3f51bdfbbf46bf6d,0xbf7fbecf3eac3f7d,0xbf6fbf42bdc93f55,0x3f1d3f7c3f18bedb,0x3e603f773f620000,0x3ea1bf31bf80bf04,
0xbf80bee63e953f7b,0x3f5f3f583e79bf3e,0x3f133f7e3f22bec4,0xbd97bf6abf71be16,0x3eb8bf27bf7fbf0e,0xbf4a3e2f3f4e3f67,0xbf7abe893ef13f80,0x3f733f393d49bf5c,
0xbf7fbe953ec43f80,0x3f623f463e48bf55,0x3f22bef1bf6dbf35,0xbf75bdc93f0e3f7b,0x3dc93f753f6d0000,0x3ef1bf22bf7bbf0e,0xbf46bf62bec43f35,0x3e953f7f3f55be48,
0xbdc9bf75bf6d8000,0xbef13f223f7b3f0e,0x3f463f623ec4bf35,0xbe95bf7fbf553e48,0xbf7fbe953ec43f80,0x3f623f463e48bf55,0x3f22bef1bf6dbf35,0xbf75bdc93f0e3f7b,
0x3f093f773f22bf0e,0x3d97bf6fbf78bd49,0x3cc9bf73bf750000,0xbf1d3f133f713f18,0x3f7c3dfbbef1bf7b,0xbf65bf31be163f67,0xbf6abf27bdc93f6d,0x3efc3f7a3f2cbf04,
0xbf583e893f463f55,0x3f7f3eb8be79bf80,0x3f803ea1be95bf80,0xbf4abf51beac3f4e,0x3e2f3f7e3f62be48,0x3ee6bf39bf7dbedb,0x3ecfbf42bf7fbec4,0xbf5f3e603f3e3f5c,
0x3f4ebedbbf55bf35,0xbf80be793e953f7f,0xbf043f3e3f7b3ec4,0x3f71be16bf22bf62,0x3f7d3eacbe48bf80,0xbf2cbf5cbef13f46,0xbf783d493f0e3f6d,0x3f673f183dc9bf75,
0x3f183f673f0ebf35,0x3d49bf78bf753dc9,0xbf5cbf2cbe483f6d,0x3eac3f7d3f46bef1,0xbe163f713f7b8000,0x3f3ebf04bf62bf22,0xbe79bf80bf553ec4,0xbedb3f4e3f7f3e95,
0xbea1bf7abf463f0e,0xbecf3f5f3f803e16,0x3dfb3f803f62bec4,0x3f13bf42bf78beac,0x3d97bf7cbf753e48,0xbf393f1d3f673f04,0xbe893f6f3f7f0000,0x3f58bee6bf4ebf2c,
0x3f73be60bf22bf55,0xbf6abefcbd493f7d,0xbf7e3cc93ef13f6d,0x3f513f273e79bf71,0x3f7f3e2fbe95bf7b,0xbf31bf4abedb3f5c,0xbf77beb83dc93f80,0x3f093f653f18bf3e,
0xbf6dbec400003f80,0x3ec43f6d3f35bf35,0x3f6d3ec40000bf80,0xbec4bf6dbf353f35,0xbf6dbec400003f80,0x3ec43f6d3f35bf35,0x3f6d3ec40000bf80,0xbec4bf6dbf353f35,
0x3ec4bf6dbf808000,0xbf6d3ec43f353f35,0xbec43f6d3f808000,0x3f6dbec4bf35bf35,0x3ec4bf6dbf808000,0xbf6d3ec43f353f35,0xbec43f6d3f808000,0x3f6dbec4bf35bf35,
0xbf273f513f753e48,0x3f80bdfbbedbbf5c,0x3efcbf6abf7f0000,0xbf7a3ea13f183f3e,0xbf653f093f463f0e,0x3f6f3e89bd49bf7d,0x3f4abf31bf62bec4,0xbf7cbd973e793f71,
0xbf42bf13be953f7b,0x3cc93f7e3f67bf04,0x3f5f3ecf3dc9bf80,0xbe60bf73bf4e3f2c,0xbee6bf58bf223f55,0xbeb83f773f80be16,0x3f1d3f393ef1bf6d,0x3e2fbf7fbf783eac,
0x3e163f713f55bf35,0x3f2cbf5cbf75bdc9,0x3e79bf80bf7b3ec4,0xbf673f183f463ef1,0x3f4e3edb3e48bf80,0xbd49bf78bf623f22,0xbf04bf3ebf0e3f6d,0xbeac3f7d3f7fbe95,
0xbf7d3eac3f0e3f35,0x3f3e3f043e95bf7f,0x3f783d49be48bf6d,0xbedbbf4ebf223f62,0xbf183f673f7b8000,0x3f80be79bef1bf46,0x3f5cbf2cbf55bec4,0xbf71be163dc93f75,
0x3f133f1d3ef1bf7b,0x3ea1bf80bf7d3edb,0xbf6fbd973dc93f6d,0x3e893f583f3ebf5c,0x3f7abefcbf22bf0e,0xbf42becfbe793f80,0xbf313f653f750000,0x3f7ebe2fbeacbf4e,
0xbf513f4a3f623e48,0x3f733cc9be16bf67,0x3eb8bf7fbf7f3ec4,0xbf773f093f2c3f04,0x3e603f5f3f46bf55,0x3f27bf6abf783d49,0xbf39bee6be953f80,0xbdfb3f7c3f71bf18,
0xbf22bef1bec43f80,0xbe953f7f3f7bbf0e,0xbdc93f753f6dbf35,0x3f62bf46bf55be48,0x3f46bf62bf6d0000,0xbf753dc93e483f55,0xbf7f3e953ec43f35,0x3ef13f223f0ebf7b,
0x3f46bf62bf6d8000,0xbf753dc93e483f55,0xbf7f3e953ec43f35,0x3ef13f223f0ebf7b,0x3f223ef13ec4bf80,0x3e95bf7fbf7b3f0e,0x3dc9bf75bf6d3f35,0xbf623f463f553e48,
0xbf6a3d973dc93f55,0x3dfb3f513f4ebf67,0x3f58bf5fbf620000,0xbf653cc93d493f5c,0x3f39bf73bf753e48,0xbf773e603e793f3e,0x3e2f3f4a3f46bf6d,0x3f42bf6fbf713e16,
0x3ecfbf7fbf7f3f0e,0xbf7e3f133f183edb,0x3f093efc3ef1bf80,0x3ee6bf80bf803f04,0x3f313ea13e95bf7b,0x3e89bf7abf783f2c,0xbf7c3f1d3f223ec4,0x3f273eb83eacbf7d,
0xbf713e793e483f35,0x3e163f3e3f46bf75,0x3d493f4e3f55bf6d,0x3f5cbf67bf623dc9,0x3edb3f043f0ebf80,0x3f18bf80bf7f3ef1,0x3f2cbf7dbf7b3ec4,0xbf783eac3e953f22,
0x3eacbf78bf7b3f35,0xbf7d3f2c3f223e95,0xbf803f183f0e3ec4,0x3f043edb3ef1bf7f,0xbf673f5c3f558000,0x3f4e3d493dc9bf62,0x3f3e3e163e48bf6d,0x3e79bf71bf753f46,
0xbf4a3cc9bdc93f55,0xbe603f653f71bf5c,0x3f42bf7cbf753ec4,0xbf6a3e893e163f2c,0x3efc3eb83ef1bf7b,0x3f13bf7fbf803f18,0xbf733f583f460000,0x3f313dfb3e79bf67,
0x3f1dbf80bf7f3f0e,0xbf7a3ee63eac3f04,0x3f273e2f3e95bf6d,0x3ecfbf77bf7d3f3e,0xbf5f3f6f3f62be48,0x3f51bd973d49bf4e,0xbea1bf09bf223f80,0xbf393f7e3f78bedb,
0xbe48bf0ebf353f80,0xbf553f7b3f6dbec4,0xbf7b3f553f350000,0x3f0e3e483ec4bf6d,0x3e483f0e3f35bf80,0x3f55bf7bbf6d3ec4,0x3f7bbf55bf350000,0xbf0ebe48bec43f6d,
0x3f7bbf55bf358000,0xbf0ebe48bec43f6d,0xbe48bf0ebf353f80,0xbf553f7b3f6dbec4,0xbf7b3f553f358000,0x3f0e3e483ec4bf6d,0x3e483f0e3f35bf80,0x3f55bf7bbf6d3ec4,
0x3dfbbf39bf623f7b,0xbf7a3f653f3ebe16,0x3f7fbf51bf220000,0xbecfbe89bf043f71,0xbefc3f6f3f7fbf55,0x3f7cbf27bedbbe79,0xbf733f093e953ec4,0x3cc93f1d3f4ebf80,
0x3f7ebf31bef1be48,0xbe60bee6bf2c3f7d,0x3d973f133f46bf80,0x3f6abf77bf5c3eac,0xbf5f3eb83dc93f0e,0xbe2f3f423f67bf78,0x3ea1bf58bf753f6d,0xbf803f4a3f183d49,
0x3f3ebf7dbf7b3f35,0xbf5c3edb3dc93ef1,0xbeacbe79bf0e3f6d,0xbf4e3f803f75bf22,0xbd493f183f55bf80,0x3f78bf71bf463e95,0x3f67bf04be48bec4,0x3e16bf2cbf623f7f,
0x3f2cbe163e48bf35,0x3f04bf67bf7f3f62,0x3f71bf78bf553ec4,0xbf183d49be953f46,0xbf803f4e3f0e8000,0x3e793eac3f22bf75,0xbedb3f5c3f7bbf6d,0x3f7dbf3ebef1bdc9,
0x3f6fbf27be95be48,0x3dfbbf13bf5c3f80,0x3e603e893f22bf6d,0x3f65bf80bf673f18,0xbf313f733f7fbf55,0x3f5fbf09be16beac,0xbf7c3f4a3ef10000,0x3d973ecf3f3ebf78,
0xbeb83f423f75bf7b,0x3f7ebf51bf043d49,0xbf7a3f773f46bec4,0x3ee63cc93edbbf4e,0xbf393ea1bdc93f0e,0xbefc3f583f7dbf71,0x3e2fbf1dbf623f80,0xbf7f3f6a3f2cbe79,
0x3e95bf22bf6d3f80,0xbf7f3f623f0ebe48,0xbef13dc9bec43f35,0xbf463f753f7bbf55,0xbf753f463ec40000,0xbdc93ef13f55bf7b,0xbf623f7f3f6dbf35,0x3f22be953e48bf0e,
0x3f75bf46bec48000,0x3dc9bef1bf553f7b,0x3f62bf7fbf6d3f35,0xbf223e95be483f0e,0x3e95bf22bf6d3f80,0xbf7f3f623f0ebe48,0xbef13dc9bec43f35,0xbf463f753f7bbf55,
0x3f7cbf7ebf463f0e,0xbea13cc9bf043f3e,0x3f6abf42be950000,0x3e89bf09bf673f7d,0x3e60befcbf623f7b,0xbf7f3f6f3f18beac,0x3f39bf65bf7f3f6d,0xbf4a3f133d493e79,
0x3e2f3dfb3f22bf55,0x3f73bf80bf5c3f2c,0xbecf3f273f75bf80,0x3f77bf58bedb3e16,0x3f7abf5fbef13e48,0x3d97beb8bf4e3f71,0x3f31bee63dc9bec4,0x3f1dbf51bf803f78,
0x3e79bd493f0ebf35,0x3f71bf7dbf623f46,0x3f18bedb3e48bec4,0x3f3ebf5cbf7f3f75,0xbf043f2c3f7bbf80,0x3f67bf4ebe953dc9,0xbe163eac3f55bf6d,0x3f80bf78bf223ef1,
0xbf783f803f55bf35,0x3eacbe163ef1bf22,0xbf4e3f673f7bbf6d,0x3f2cbf043dc9be95,0xbf5c3f3e3e488000,0xbedb3f183f75bf7f,0xbf7d3f713f0ebec4,0xbd493e793f46bf62,
0xbf7f3f7c3f22bf0e,0xbcc93dfb3f3ebf4e,0xbf773f6f3ef1bec4,0xbe603ea13f5cbf67,0xbf653f583e95be48,0xbecf3efc3f71bf78,0xbf4a3f393dc90000,0xbf133f273f7dbf80,
0x3d97be2fbf463f55,0xbf803f7e3f2cbf18,0x3e89beb8bf623f6d,0xbf7a3f733f04bedb,0x3ee6bf09bf753f7b,0xbf6a3f5f3eacbe79,0x3f1dbf31bf7f3f80,0xbf513f423e16bd49,
0x3f803f80,0xbf80bf80,0x3f803f80,0xbf80bf80,0x3f803f80,0xbf80bf80,0x3f803f80,0xbf80bf80,
0xbf80bf8080008000,0x3f803f8080008000,0xbf80bf8080008000,0x3f803f8080008000,0xbf80bf8080008000,0x3f803f8080008000,0xbf80bf8080008000,0x3f803f8080008000,
0xbee6bf09bf62bf55,0x3ecf3efc3f673f5c,0xbf1dbf31bf46bf35,0x3f133f273f4e3f3e,0xbd97be2fbf7fbf7b,0x3cc93dfb3f803f7d,0xbe89beb8bf75bf6d,0x3e603ea13f783f71,
0x3f653f58bef1bf0e,0xbf6abf5f3edb3f04,0x3f4a3f39bf22bf35,0xbf51bf423f183f2c,0x3f7f3f7cbdc9be48,0xbf80bf7e3d493e16,0x3f773f6fbe95bec4,0xbf7abf733e793eac,
0x3f043f2c3f553f35,0xbedbbf18bf62bf46,0x3e163eac3f7b3f6d,0xbd49be79bf7fbf75,0x3f783f803e480000,0xbf71bf7dbe95bdc9,0x3f4e3f673f0e3ec4,0xbf3ebf5cbf22bef1,
0xbf5cbf3e3f0e3f35,0x3f673f4ebef1bf22,0xbf7dbf713e483ec4,0x3f803f78bdc9be95,0xbe79bd493f7b3f80,0x3eac3e16bf75bf7f,0xbf18bedb3f553f6d,0x3f2c3f04bf46bf62,
0xbe60befcbf75bf55,0x3d973eb83f7d3f67,0xbf39bf65bf22bec4,0x3f1d3f513f3e3f04,0xbf7cbf7ebdc93e48,0x3f733f803e79bd49,0xbf6abf423ef13f35,0x3f773f58beacbf18,
0x3f7a3f5fbe95bf0e,0xbf7fbf6f3e163edb,0x3f313ee6bf46bf6d,0xbf4abf133f2c3f5c,0x3e2fbdfbbf7fbf7b,0xbea1bcc93f783f80,0xbecfbf27bf62bf35,0x3e893f093f713f4e,
0x3ef13dc9bf6dbf80,0xbf22be953f553f7b,0x3f753f46bec4bf35,0xbf7fbf623e483f0e,0x3f623f7f3ec40000,0xbf46bf75bf0ebe48,0x3e953f223f6d3f35,0xbdc9bef1bf7bbf55,
0x3f623f7f3ec48000,0xbf46bf75bf0ebe48,0x3e953f223f6d3f35,0xbdc9bef1bf7bbf55,0xbef1bdc93f6d3f80,0x3f223e95bf55bf7b,0xbf75bf463ec43f35,0x3f7f3f62be48bf0e,
0xbf39bea13f463f7b,0x3f5f3f09bf18bf67,0x3e2f3f1d3f753f35,0x3d97becfbf80bf5c,0xbeb8bf42bf62bf0e,0x3dfb3f133f783f3e,0xbf7abf77bdc93ec4,0x3f653f803eacbe16,
0xbf31bf73bf22be48,0x3efc3f583f4e3edb,0xbf7cbf4a3e953f35,0x3f7f3f6abd49bf04,0x3f6f3f27bef1bf55,0xbf7ebf513e793f2c,0x3e60be89bf7fbf6d,0xbee63cc93f713f7d,
0x3f803f4ebe48bf35,0xbf78bf71bdc93ef1,0x3edb3f5c3f553ec4,0xbe16bf2cbf75bf22,0xbf3ebf7dbf0e0000,0x3f043f673f463e95,0x3eacbe79bf7bbf6d,0xbf18bd493f623f7f,
0x3d493f183f7b3f35,0x3e79beacbf7fbf62,0xbf67bf043f0e3f6d,0x3f7d3f3ebe95bf46,0x3f2c3e16bf55bf80,0xbf5cbedb3f223f75,0x3f713f783e48bec4,0xbf4ebf80bef13dc9,
0xbefcbf6fbf46be48,0x3e2f3f423f713f04,0xbf73bf093ef13f6d,0x3f803f4abe16bf3e,0x3dfb3f393f753f0e,0x3e60bee6bf80bf4e,0x3f7f3f51bdc9bf35,0xbf6abf77be793edb,
0x3f5f3eb8bf22bf7b,0xbf7cbf273eac3f5c,0xbea1bf58bf62bec4,0xbcc93f1d3f7d3f2c,0xbf7ebf313e953f55,0x3f7a3f653d49bf18,0xbd973f133f7f3f35,0x3ecfbe89bf78bf67,
0xbf55be483f353f80,0x3f7b3f0ebec4bf6d,0xbf0ebf7bbf350000,0x3e483f553f6d3ec4,0x3f553e48bf35bf80,0xbf7bbf0e3ec43f6d,0x3f0e3f7b3f350000,0xbe48bf55bf6dbec4,
0xbf0ebf7bbf358000,0x3e483f553f6d3ec4,0x3f553e48bf35bf80,0xbf7bbf0e3ec43f6d,0x3f0e3f7b3f358000,0xbe48bf55bf6dbec4,0xbf55be483f353f80,0x3f7b3f0ebec4bf6d,
0x3f5f3f6f3e95bf0e,0xbf13bf7fbf2c3e16,0x3ea1bf09bf7fbf35,0xbf313dfb3f5c3f71,0xbf1dbf80bf223e48,0x3e603f653f673e79,0xbf273e2f3f623f6d,0x3f6a3e89bf18bf80,
0xbefc3eb83f753f55,0x3f513d97bf3ebf7d,0x3f733f583dc9bf35,0xbf39bf7ebf043eac,0x3f4a3cc9bf46bf7b,0xbf7abee63edb3f78,0xbf42bf7cbef13ec4,0x3ecf3f773f4e3d49,
0x3edbbf04bf7bbf35,0xbf4e3d493f463f75,0x3f2c3f7d3f0ebec4,0xbe79bf71bf62bdc9,0x3eac3f783f550000,0x3e16bf3ebf7fbef1,0xbf80bf183e483f6d,0x3f5c3f673e95bf22,
0x3f673f5c3e48bf35,0xbf18bf80bf223e95,0xbf3e3e163f553f6d,0x3f783eacbef1bf7f,0xbf71be793f0e3f80,0x3f7d3f2cbdc9bf62,0x3d49bf4ebf7bbec4,0xbf043edb3f753f46,
0xbf39bf73bef13f0e,0x3e893f7a3f5cbd49,0xbe2f3f4a3f7f3ec4,0x3f27beb8bf67bf4e,0x3f6a3d97bf22bf7b,0xbf7ebf133e163f71,0xbf58bf5fbe953f35,0x3ee63f803f3ebe79,
0x3f31bea1bf62bf55,0xbf77be603f043f80,0xbf7cbf1d3dc93f6d,0x3f423f6f3edbbf18,0x3ecf3f7f3f46be48,0x3dfbbf51bf7dbeac,0x3f09befcbf75bf35,0xbf65bcc93f2c3f78,
0x3f7f3e95bec4bf80,0xbf62bf46be483f55,0xbf223ef13f6d3f35,0x3f753dc9bf0ebf7b,0xbdc9bf75bf6d0000,0xbef13f223f7b3f0e,0x3f463f623ec4bf35,0xbe95bf7fbf553e48,
0x3dc93f753f6d8000,0x3ef1bf22bf7bbf0e,0xbf46bf62bec43f35,0x3e953f7f3f55be48,0x3f7f3e95bec4bf80,0xbf62bf46be483f55,0xbf223ef13f6d3f35,0x3f753dc9bf0ebf7b,
0x3e60bf5fbf7fbe48,0xbf423ecf3f5c3f3e,0xbf393ee63f623f35,0x3f7e3e2fbedbbf7d,0xbf51bf4abe953f55,0x3ea13f803f4ebeac,0x3eb83f7f3f46bec4,0x3e89bf58bf80be79,
0x3f7a3efcbdc9bf7b,0xbf27bf6abf043f2c,0xbf31bf65bef13f35,0x3dfb3f7c3f67be16,0x3f13bf1dbf75bf0e,0xbf733cc93f183f71,0xbf6f3d973f223f6d,0x3f773f09bd49bf78,
0xbf18bf67bf0e3f35,0xbd493f783f75bdc9,0x3f5c3f2c3e48bf6d,0xbeacbf7dbf463ef1,0x3e16bf71bf7b0000,0xbf3e3f043f623f22,0x3e793f803f55bec4,0x3edbbf4ebf7fbe95,
0x3f4ebedbbf55bf35,0xbf80be793e953f7f,0xbf043f3e3f7b3ec4,0x3f71be16bf22bf62,0x3f7d3eacbe48bf80,0xbf2cbf5cbef13f46,0xbf783d493f0e3f6d,0x3f673f183dc9bf75,
0xbf65bf09bdc93f7b,0x3eb83f773f3ebf18,0x3f4a3f313e95bf6d,0xbe2fbf7fbf5c3edb,0xbf27bf51bef13f55,0xbcc93f7e3f71be79,0x3efc3f6a3f22bf35,0x3e60bf73bf7d3d49,
0x3ee6bf58bf7fbe48,0xbf6f3e893f2c3f4e,0xbf1d3f393f753ec4,0x3f7cbd97bf04bf67,0x3f42bf13bf62bf0e,0xbf80bdfb3eac3f78,0xbf5f3ecf3f463f35,0x3f7a3ea1be16bf80,
0xbf6dbec400003f80,0x3ec43f6d3f35bf35,0x3f6d3ec40000bf80,0xbec4bf6dbf353f35,0xbf6dbec400003f80,0x3ec43f6d3f35bf35,0x3f6d3ec40000bf80,0xbec4bf6dbf353f35,
0x3ec4bf6dbf808000,0xbf6d3ec43f353f35,0xbec43f6d3f808000,0x3f6dbec4bf35bf35,0x3ec4bf6dbf808000,0xbf6d3ec43f353f35,0xbec43f6d3f808000,0x3f6dbec4bf35bf35,
0xbf7f3e2f3ef13f55,0x3f393f1d3eacbf78,0x3f77beb8bf22bf35,0xbf58bee6be163f80,0xbf73be603dc93f7b,0x3ecf3f5f3f2cbf4e,0x3f7e3cc9be95bf6d,0xbf13bf42bf043f67,
0xbd97bf7cbf623f0e,0xbf313f4a3f713e79,0x3e893f6f3f46bf35,0x3f09bf65bf7dbd49,0x3ea1bf7abf7f3e48,0xbf6a3efc3f3e3f18,0xbdfb3f803f75bec4,0x3f51bf27bf5cbedb,
0xbf7d3eac3f0e3f35,0x3f3e3f043e95bf7f,0x3f783d49be48bf6d,0xbedbbf4ebf223f62,0xbf183f673f7b0000,0x3f80be79bef1bf46,0x3f5cbf2cbf55bec4,0xbf71be163dc93f75,
0xbe16bf71bf553f35,0xbf2c3f5c3f753dc9,0xbe793f803f7bbec4,0x3f67bf18bf46bef1,0xbf4ebedbbe483f80,0x3d493f783f62bf22,0x3f043f3e3f0ebf6d,0x3eacbf7dbf7f3e95,
0xbf7c3dfb3e953f55,0x3ee63f393f18bf71,0x3f6abf27bf46bec4,0xbf5fbe60bd493f78,0xbf093f773f7fbe48,0x3f7fbeb8bf04bf2c,0xbcc9bf73bf623f35,0xbf4a3f513f673e16,
0x3e2fbf7ebf753f0e,0xbf653f313f4e3eac,0x3ecf3f423f22bf6d,0x3efcbf7abf803e79,0xbf58be89bdc93f7b,0x3d973f6f3f5cbf3e,0x3f80bea1bef1bf35,0xbf1dbf13bedb3f7d,
0x3f223ef13ec4bf80,0x3e95bf7fbf7b3f0e,0x3dc9bf75bf6d3f35,0xbf623f463f553e48,0xbf463f623f6d0000,0x3f75bdc9be48bf55,0x3f7fbe95bec4bf35,0xbef1bf22bf0e3f7b,
0xbf463f623f6d8000,0x3f75bdc9be48bf55,0x3f7fbe95bec4bf35,0xbef1bf22bf0e3f7b,0xbf22bef1bec43f80,0xbe953f7f3f7bbf0e,0xbdc93f753f6dbf35,0x3f62bf46bf55be48,
0x3eb83f273f22bf7b,0x3f1dbf7cbf7d3eac,0xbf7a3e893e953f35,0x3ea13f313f2cbf78,0xbf803ee63ef13f0e,0x3efc3f093f04bf80,0x3f13bf7ebf7f3ec4,0xbf7f3ecf3edb3f18,
0xbf6f3f423f463e48,0x3f4a3e2f3e16bf71,0x3e60bf77bf753f35,0xbf733f393f3e3e79,0x3cc9bf65bf623f55,0xbf5f3f583f5c3d49,0x3f513dfb3dc9bf6d,0x3d97bf6abf673f4e,
0xbeac3f783f7bbf35,0x3f7dbf2cbf22be95,0x3f80bf18bf0ebec4,0xbf04bedbbef13f7f,0x3f67bf5cbf550000,0xbf4ebd49bdc93f62,0xbf3ebe16be483f6d,0xbe793f713f75bf46,
0xbf713e793e483f35,0x3e163f3e3f46bf75,0x3d493f4e3f55bf6d,0x3f5cbf67bf623dc9,0x3edb3f043f0ebf80,0x3f18bf80bf7f3ef1,0x3f2cbf7dbf7b3ec4,0xbf783eac3e953f22,
0xbf7e3f393f223e48,0x3f093ea13edbbf78,0x3d97bf51bf623f6d,0xbf6f3f5f3f4ebd49,0x3f77becfbe95bf0e,0xbe2fbf27bf3e3f7d,0xbee63f7a3f7fbf35,0x3f80bf1dbf04beac,
0xbdfbbf31bf463f7b,0xbf583f733f67be79,0x3f7fbf13bef1bec4,0xbeb8befcbf183f80,0xbe893f6a3f75bf55,0x3f7cbf42bf2cbe16,0xbf653e603dc93f35,0xbcc93f4a3f5cbf71,
0xbe48bf0ebf353f80,0xbf553f7b3f6dbec4,0xbf7b3f553f350000,0x3f0e3e483ec4bf6d,0x3e483f0e3f35bf80,0x3f55bf7bbf6d3ec4,0x3f7bbf55bf350000,0xbf0ebe48bec43f6d,
0x3f7bbf55bf358000,0xbf0ebe48bec43f6d,0xbe48bf0ebf353f80,0xbf553f7b3f6dbec4,0xbf7b3f553f358000,0x3f0e3e483ec4bf6d,0x3e483f0e3f35bf80,0x3f55bf7bbf6d3ec4,
0x3f4abf80bf753f0e,0xbf583ea13d493f18,0x3f42be2f3dc9bf35,0x3eb8bf5fbf783f67,0xbf773f6a3f46be48,0x3f133d973eacbf5c,0xbee6be60bef13f6d,0xbf313f7e3f7dbf2c,
0x3f1d3cc93e95bf55,0x3f09bf73bf803f4e,0xbf273f7c3f7fbf35,0x3f6fbefcbe79bedb,0xbe89becfbf223f7b,0xbf513f7f3f71bf04,0x3f65bf7abf623ec4,0xbf393dfbbe163f3e,
0x3f2cbe163e48bf35,0x3f04bf67bf7f3f62,0x3f71bf78bf553ec4,0xbf183d49be953f46,0xbf803f4e3f0e0000,0x3e793eac3f22bf75,0xbedb3f5c3f7bbf6d,0x3f7dbf3ebef1bdc9,
0xbf3e3f7d3f7bbf35,0x3f5cbedbbdc9bef1,0x3eac3e793f0ebf6d,0x3f4ebf80bf753f22,0x3d49bf18bf553f80,0xbf783f713f46be95,0xbf673f043e483ec4,0xbe163f2c3f62bf7f,
0xbf6a3f7f3f62bf0e,0x3f1dbe2f3e79bf2c,0xbf583efc3dc93ec4,0xbea13f393f71bf7d,0xbcc9bee6bf463f7b,0xbf773f7a3f4ebedb,0x3f51bf7ebf753f35,0xbf423eb8bd493f04,
0xbecfbd97bef13f55,0xbf4a3f7c3f78bf3e,0x3f09bf5fbf7f3f6d,0xbf733f313eac3e16,0x3f80bf65bf223e48,0xbe89be60bf183f67,0x3f13bdfb3e95bf35,0x3f27bf6fbf803f5c,
0xbe953f223f6dbf80,0x3f7fbf62bf0e3e48,0x3ef1bdc93ec4bf35,0x3f46bf75bf7b3f55,0x3f75bf46bec40000,0x3dc9bef1bf553f7b,0x3f62bf7fbf6d3f35,0xbf223e95be483f0e,
0xbf753f463ec48000,0xbdc93ef13f55bf7b,0xbf623f7f3f6dbf35,0x3f22be953e48bf0e,0xbe953f223f6dbf80,0x3f7fbf62bf0e3e48,0x3ef1bdc93ec4bf35,0x3f46bf75bf7b3f55,
0xbf513f1d3dc93e48,0xbee63f313f78bf80,0xbeb83d97bef13f35,0xbf5f3f7a3f71bf4e,0xbf583f773f75bf55,0x3f27becf3e16bedb,0xbf803f733f22bec4,0x3dfb3e2f3f2cbf5c,
0x3f13bf4abf7f3f7b,0xbf653f393e793d49,0x3f6fbf7fbf623f35,0xbefc3e60beac3f18,0xbf093e89be953f0e,0xbf423f6a3f7dbf67,0x3cc9bea1bf463f6d,0xbf7e3f7c3f3ebf04,
0x3f78bf80bf553f35,0xbeac3e16bef13f22,0x3f4ebf67bf7b3f6d,0xbf2c3f04bdc93e95,0x3f5cbf3ebe480000,0x3edbbf18bf753f7f,0x3f7dbf71bf0e3ec4,0x3d49be79bf463f62,
0x3e79bd493f0ebf35,0x3f71bf7dbf623f46,0x3f18bedb3e48bec4,0x3f3ebf5cbf7f3f75,0xbf043f2c3f7bbf80,0x3f67bf4ebe953dc9,0xbe163eac3f55bf6d,0x3f80bf78bf223ef1,
0xbf423f513f7fbf7b,0x3f31bf1d3d49be16,0xbf5f3f6a3f75bf6d,0x3f09bee63e79beac,0xbf733f7a3f62bf55,0x3eb8be893edbbf04,0xbf7e3f803f46bf35,0x3e2fbd973f18bf2c,
0xbf273f13bdc93e48,0xbf393f4a3f80bf7d,0xbefc3ecfbe953ec4,0xbf583f653f78bf71,0xbea13e60bef13f0e,0xbf6f3f773f67bf5c,0xbdfb3cc9bf223f35,0xbf7c3f7f3f4ebf3e,
0x3f803f80,0xbf80bf80,0x3f803f80,0xbf80bf80,0x3f803f80,0xbf80bf80,0x3f803f80,0xbf80bf80,
0xbf80bf8080008000,0x3f803f8080008000,0xbf80bf8080008000,0x3f803f8080008000,0xbf80bf8080008000,0x3f803f8080008000,0xbf80bf8080008000,0x3f803f8080008000,
0x3ea13e60bf75bf7b,0xbeb8be893f713f78,0x3dfb3cc9bf7fbf80,0xbe2fbd973f7d3f80,0x3f273f13bf46bf55,0xbf31bf1d3f3e3f4e,0x3efc3ecfbf62bf6d,0xbf09bee63f5c3f67,
0x3f733f7a3e953e48,0xbf6fbf77beacbe79,0x3f7e3f803dc98000,0xbf7cbf7fbe16bd49,0x3f423f513f223f0e,0xbf39bf4abf2cbf18,0x3f5f3f6a3ef13ec4,0xbf58bf65bf04bedb,
0xbf5cbf3e3f0e3f35,0x3f673f4ebef1bf22,0xbf7dbf713e483ec4,0x3f803f78bdc9be95,0xbe79bd493f7b3f80,0x3eac3e16bf75bf7f,0xbf18bedb3f553f6d,0x3f2c3f04bf46bf62,
0xbf04bf2cbf55bf35,0x3edb3f183f623f46,0xbe16beacbf7bbf6d,0x3d493e793f7f3f75,0xbf78bf80be488000,0x3f713f7d3e953dc9,0xbf4ebf67bf0ebec4,0x3f3e3f5c3f223ef1,
0x3f583f773ef13e48,0xbf42bf6abf18beac,0x3f803f73bdc9bec4,0xbf7ebf7cbd493e79,0x3f513f1dbf22bf55,0xbf65bf393f043f3e,0x3eb83d97bf75bf80,0xbefcbe603f673f7d,
0xbf09be893f623f7b,0x3f273ecfbf4ebf71,0x3cc93ea13f7f3f6d,0x3dfbbe2fbf80bf78,0x3f133f4a3f463f0e,0xbee6bf31bf5cbf2c,0x3f6f3f7f3e958000,0xbf5fbf7abedbbe16,
0xbef1bdc93f6d3f80,0x3f223e95bf55bf7b,0xbf75bf463ec43f35,0x3f7f3f62be48bf0e,0xbf62bf7fbec40000,0x3f463f753f0e3e48,0xbe95bf22bf6dbf35,0x3dc93ef13f7b3f55,
0xbf62bf7fbec48000,0x3f463f753f0e3e48,0xbe95bf22bf6dbf35,0x3dc93ef13f7b3f55,0x3ef13dc9bf6dbf80,0xbf22be953f553f7b,0x3f753f46bec4bf35,0xbf7fbf623e483f0e,
0x3f803f65bdc9bf0e,0xbf77bf7abe163eac,0x3f133dfbbf62bf80,0xbf42beb83f3e3f78,0xbecf3d973f753f7b,0x3f1d3e2fbf5cbf80,0x3f093f5f3f463ec4,0xbea1bf39bf67bf18,
0xbcc93ee63f7f3f55,0x3e89be60bf7dbf71,0x3f513f7e3ef18000,0xbf27bf6fbf2cbe79,0xbf6abf7fbe953e48,0x3f4a3f7c3f043d49,0xbf58befc3f223f6d,0x3f733f31bedbbf4e,
0xbd49bf18bf7bbf35,0xbe793eac3f7f3f62,0x3f673f04bf0ebf6d,0xbf7dbf3e3e953f46,0xbf2cbe163f553f80,0x3f5c3edbbf22bf75,0xbf71bf78be483ec4,0x3f4e3f803ef1bdc9,
0x3f803f4ebe48bf35,0xbf78bf71bdc93ef1,0x3edb3f5c3f553ec4,0xbe16bf2cbf75bf22,0xbf3ebf7dbf0e8000,0x3f043f673f463e95,0x3eacbe79bf7bbf6d,0xbf18bd493f623f7f,
0xbf77bf6abdc93f0e,0x3f513f7f3edbbe79,0xbee63e603f753f6d,0x3f393dfbbf4ebf80,0x3f4a3f803ef1be48,0xbf09bf73bf3ebe16,0x3f423e2fbf46bf80,0xbf6fbefc3f043f71,
0x3e89becfbf7fbf55,0xbf133d973f673f78,0xbf65bf7abe953ec4,0x3f313f7e3f18bd49,0xbf1d3cc93f623f7b,0x3f583ea1bf2cbf7d,0x3f273f7c3f228000,0xbeb8bf5fbf5cbeac,
0xbf55be483f353f80,0x3f7b3f0ebec4bf6d,0xbf0ebf7bbf350000,0x3e483f553f6d3ec4,0x3f553e48bf35bf80,0xbf7bbf0e3ec43f6d,0x3f0e3f7b3f350000,0xbe48bf55bf6dbec4,
0xbf0ebf7bbf358000,0x3e483f553f6d3ec4,0x3f553e48bf35bf80,0xbf7bbf0e3ec43f6d,0x3f0e3f7b3f358000,0xbe48bf55bf6dbec4,0xbf55be483f353f80,0x3f7b3f0ebec4bf6d,
0x3e893f6a3f623e48,0x3e2fbf27bf80bf18,0x3f653e60bf22bf80,0xbf80bf1d3e793f67,0x3dfbbf31bf7fbf0e,0xbf093ea13f713f5c,0xbf7fbf133e953f6d,0x3f6f3f5f3e16bf2c,
0xbf77becf3ef13f7b,0x3f7c3f42bd49bf4e,0x3ee63f7a3f468000,0xbcc9bf4abf78bedb,0x3f7e3f39bdc9bf55,0xbf58bf73beac3f04,0xbd97bf51bf75bec4,0xbeb83efc3f7d3f3e,
0x3f673f5c3e48bf35,0xbf18bf80bf223e95,0xbf3e3e163f553f6d,0x3f783eacbef1bf7f,0xbf71be793f0e3f80,0x3f7d3f2cbdc9bf62,0x3d49bf4ebf7bbec4,0xbf043edb3f753f46,
0xbedb3f043f7b3f35,0x3f4ebd49bf46bf75,0xbf2cbf7dbf0e3ec4,0x3e793f713f623dc9,0xbeacbf78bf558000,0xbe163f3e3f7f3ef1,0x3f803f18be48bf6d,0xbf5cbf67be953f22,
0x3f803ee6be95bf7b,0xbf5fbf58be793f3e,0xbf13bf7ebf223ec4,0x3d973f6a3f713e16,0xbeb83f273f7f3f0e,0x3f4abe2fbf4ebf67,0x3f7a3e89bef1bf80,0xbf73bf39bd493f5c,
0x3cc93f653f753e48,0x3efcbf09bf78bf2c,0x3f51bdfbbf46bf6d,0xbf7fbecf3eac3f7d,0xbf6fbf42bdc93f55,0x3f1d3f7c3f18bedb,0x3e603f773f628000,0x3ea1bf31bf80bf04,
0xbf7fbe953ec43f80,0x3f623f463e48bf55,0x3f22bef1bf6dbf35,0xbf75bdc93f0e3f7b,0x3dc93f753f6d0000,0x3ef1bf22bf7bbf0e,0xbf46bf62bec43f35,0x3e953f7f3f55be48,
0xbdc9bf75bf6d8000,0xbef13f223f7b3f0e,0x3f463f623ec4bf35,0xbe95bf7fbf553e48,0xbf7fbe953ec43f80,0x3f623f463e48bf55,0x3f22bef1bf6dbf35,0xbf75bdc93f0e3f7b,
0xbf583e893f463f55,0x3f7f3eb8be79bf80,0x3f803ea1be95bf80,0xbf4abf51beac3f4e,0x3e2f3f7e3f62be48,0x3ee6bf39bf7dbedb,0x3ecfbf42bf7fbec4,0xbf5f3e603f3e3f5c,
0xbf09bf77bf223f0e,0xbd973f6f3f783d49,0xbcc93f733f758000,0x3f1dbf13bf71bf18,0xbf7cbdfb3ef13f7b,0x3f653f313e16bf67,0x3f6a3f273dc9bf6d,0xbefcbf7abf2c3f04,
0xbf4e3edb3f553f35,0x3f803e79be95bf7f,0x3f04bf3ebf7bbec4,0xbf713e163f223f62,0xbf7dbeac3e483f80,0x3f2c3f5c3ef1bf46,0x3f78bd49bf0ebf6d,0xbf67bf18bdc93f75,
0xbf18bf67bf0e3f35,0xbd493f783f75bdc9,0x3f5c3f2c3e48bf6d,0xbeacbf7dbf463ef1,0x3e16bf71bf7b8000,0xbf3e3f043f623f22,0x3e793f803f55bec4,0x3edbbf4ebf7fbe95,
0xbf733e603f223f55,0x3f6a3efc3d49bf7d,0x3f7ebcc9bef1bf6d,0xbf51bf27be793f71,0xbf7fbe2f3e953f7b,0x3f313f4a3edbbf5c,0x3f773eb8bdc9bf80,0xbf09bf65bf183f3e,
0xbea1bf7abf463f0e,0xbecf3f5f3f803e16,0x3dfb3f803f62bec4,0x3f13bf42bf78beac,0x3d97bf7cbf753e48,0xbf393f1d3f673f04,0xbe893f6f3f7f8000,0x3f58bee6bf4ebf2c,
0xbf6dbec400003f80,0x3ec43f6d3f35bf35,0x3f6d3ec40000bf80,0xbec4bf6dbf353f35,0xbf6dbec400003f80,0x3ec43f6d3f35bf35,0x3f6d3ec40000bf80,0xbec4bf6dbf353f35,
0x3ec4bf6dbf808000,0xbf6d3ec43f353f35,0xbec43f6d3f808000,0x3f6dbec4bf35bf35,0x3ec4bf6dbf808000,0xbf6d3ec43f353f35,0xbec43f6d3f808000,0x3f6dbec4bf35bf35,
0xbf42bf13be953f7b,0x3cc93f7e3f67bf04,0x3f5f3ecf3dc9bf80,0xbe60bf73bf4e3f2c,0xbee6bf58bf223f55,0xbeb83f773f80be16,0x3f1d3f393ef1bf6d,0x3e2fbf7fbf783eac,
0x3f27bf51bf75be48,0xbf803dfb3edb3f5c,0xbefc3f6a3f7f8000,0x3f7abea1bf18bf3e,0x3f65bf09bf46bf0e,0xbf6fbe893d493f7d,0xbf4a3f313f623ec4,0x3f7c3d97be79bf71,
0xbe16bf71bf553f35,0xbf2c3f5c3f753dc9,0xbe793f803f7bbec4,0x3f67bf18bf46bef1,0xbf4ebedbbe483f80,0x3d493f783f62bf22,0x3f043f3e3f0ebf6d,0x3eacbf7dbf7f3e95,
0x3f7dbeacbf0ebf35,0xbf3ebf04be953f7f,0xbf78bd493e483f6d,0x3edb3f4e3f22bf62,0x3f18bf67bf7b8000,0xbf803e793ef13f46,0xbf5c3f2c3f553ec4,0x3f713e16bdc9bf75,
0x3f51bf4abf62be48,0xbf73bcc93e163f67,0xbeb83f7f3f7fbec4,0x3f77bf09bf2cbf04,0xbe60bf5fbf463f55,0xbf273f6a3f78bd49,0x3f393ee63e95bf80,0x3dfbbf7cbf713f18,
0x3f133f1d3ef1bf7b,0x3ea1bf80bf7d3edb,0xbf6fbd973dc93f6d,0x3e893f583f3ebf5c,0x3f7abefcbf22bf0e,0xbf42becfbe793f80,0xbf313f653f758000,0x3f7ebe2fbeacbf4e,
0xbf22bef1bec43f80,0xbe953f7f3f7bbf0e,0xbdc93f753f6dbf35,0x3f62bf46bf55be48,0x3f46bf62bf6d0000,0xbf753dc93e483f55,0xbf7f3e953ec43f35,0x3ef13f223f0ebf7b,
0x3f46bf62bf6d8000,0xbf753dc93e483f55,0xbf7f3e953ec43f35,0x3ef13f223f0ebf7b,0x3f223ef13ec4bf80,0x3e95bf7fbf7b3f0e,0x3dc9bf75bf6d3f35,0xbf623f463f553e48,
0x3ecfbf7fbf7f3f0e,0xbf7e3f133f183edb,0x3f093efc3ef1bf80,0x3ee6bf80bf803f04,0x3f313ea13e95bf7b,0x3e89bf7abf783f2c,0xbf7c3f1d3f223ec4,0x3f273eb83eacbf7d,
0x3f6abd97bdc9bf55,0xbdfbbf51bf4e3f67,0xbf583f5f3f628000,0x3f65bcc9bd49bf5c,0xbf393f733f75be48,0x3f77be60be79bf3e,0xbe2fbf4abf463f6d,0xbf423f6f3f71be16,
0x3f71be79be48bf35,0xbe16bf3ebf463f75,0xbd49bf4ebf553f6d,0xbf5c3f673f62bdc9,0xbedbbf04bf0e3f80,0xbf183f803f7fbef1,0xbf2c3f7d3f7bbec4,0x3f78beacbe95bf22,
0xbeac3f783f7bbf35,0x3f7dbf2cbf22be95,0x3f80bf18bf0ebec4,0xbf04bedbbef13f7f,0x3f67bf5cbf558000,0xbf4ebd49bdc93f62,0xbf3ebe16be483f6d,0xbe793f713f75bf46,
0xbf1d3f803f7fbf0e,0x3f7abee6beacbf04,0xbf27be2fbe953f6d,0xbecf3f773f7dbf3e,0x3f5fbf6fbf623e48,0xbf513d97bd493f4e,0x3ea13f093f22bf80,0x3f39bf7ebf783edb,
0xbf4a3cc9bdc93f55,0xbe603f653f71bf5c,0x3f42bf7cbf753ec4,0xbf6a3e893e163f2c,0x3efc3eb83ef1bf7b,0x3f13bf7fbf803f18,0xbf733f583f468000,0x3f313dfb3e79bf67,
0xbe48bf0ebf353f80,0xbf553f7b3f6dbec4,0xbf7b3f553f350000,0x3f0e3e483ec4bf6d,0x3e483f0e3f35bf80,0x3f55bf7bbf6d3ec4,0x3f7bbf55bf350000,0xbf0ebe48bec43f6d,
0x3f7bbf55bf358000,0xbf0ebe48bec43f6d,0xbe48bf0ebf353f80,0xbf553f7b3f6dbec4,0xbf7b3f553f358000,0x3f0e3e483ec4bf6d,0x3e483f0e3f35bf80,0x3f55bf7bbf6d3ec4,
0x3f7ebf31bef1be48,0xbe60bee6bf2c3f7d,0x3d973f133f46bf80,0x3f6abf77bf5c3eac,0xbf5f3eb83dc93f0e,0xbe2f3f423f67bf78,0x3ea1bf58bf753f6d,0xbf803f4a3f183d49,
0xbdfb3f393f62bf7b,0x3f7abf65bf3e3e16,0xbf7f3f513f228000,0x3ecf3e893f04bf71,0x3efcbf6fbf7f3f55,0xbf7c3f273edb3e79,0x3f73bf09be95bec4,0xbcc9bf1dbf4e3f80,
0xbf3e3f7d3f7bbf35,0x3f5cbedbbdc9bef1,0x3eac3e793f0ebf6d,0x3f4ebf80bf753f22,0x3d49bf18bf553f80,0xbf783f713f46be95,0xbf673f043e483ec4,0xbe163f2c3f62bf7f,
0xbf2c3e16be483f35,0xbf043f673f7fbf62,0xbf713f783f55bec4,0x3f18bd493e95bf46,0x3f80bf4ebf0e8000,0xbe79beacbf223f75,0x3edbbf5cbf7b3f6d,0xbf7d3f3e3ef13dc9,
0x3eb8bf42bf753f7b,0xbf7e3f513f04bd49,0x3f7abf77bf463ec4,0xbee6bcc9bedb3f4e,0x3f39bea13dc9bf0e,0x3efcbf58bf7d3f71,0xbe2f3f1d3f62bf80,0x3f7fbf6abf2c3e79,
0x3f6fbf27be95be48,0x3dfbbf13bf5c3f80,0x3e603e893f22bf6d,0x3f65bf80bf673f18,0xbf313f733f7fbf55,0x3f5fbf09be16beac,0xbf7c3f4a3ef18000,0x3d973ecf3f3ebf78,
0x3e95bf22bf6d3f80,0xbf7f3f623f0ebe48,0xbef13dc9bec43f35,0xbf463f753f7bbf55,0xbf753f463ec40000,0xbdc93ef13f55bf7b,0xbf623f7f3f6dbf35,0x3f22be953e48bf0e,
0x3f75bf46bec48000,0x3dc9bef1bf553f7b,0x3f62bf7fbf6d3f35,0xbf223e95be483f0e,0x3e95bf22bf6d3f80,0xbf7f3f623f0ebe48,0xbef13dc9bec43f35,0xbf463f753f7bbf55,
0x3e2f3dfb3f22bf55,0x3f73bf80bf5c3f2c,0xbecf3f273f75bf80,0x3f77bf58bedb3e16,0x3f7abf5fbef13e48,0x3d97beb8bf4e3f71,0x3f31bee63dc9bec4,0x3f1dbf51bf803f78,
0xbf7c3f7e3f46bf0e,0x3ea1bcc93f04bf3e,0xbf6a3f423e958000,0xbe893f093f67bf7d,0xbe603efc3f62bf7b,0x3f7fbf6fbf183eac,0xbf393f653f7fbf6d,0x3f4abf13bd49be79,
0xbe793d49bf0e3f35,0xbf713f7d3f62bf46,0xbf183edbbe483ec4,0xbf3e3f5c3f7fbf75,0x3f04bf2cbf7b3f80,0xbf673f4e3e95bdc9,0x3e16beacbf553f6d,0xbf803f783f22bef1,
0x3f78bf80bf553f35,0xbeac3e16bef13f22,0x3f4ebf67bf7b3f6d,0xbf2c3f04bdc93e95,0x3f5cbf3ebe488000,0x3edbbf18bf753f7f,0x3f7dbf71bf0e3ec4,0x3d49be79bf463f62,
0xbd973e2f3f46bf55,0x3f80bf7ebf2c3f18,0xbe893eb83f62bf6d,0x3f7abf73bf043edb,0xbee63f093f75bf7b,0x3f6abf5fbeac3e79,0xbf1d3f313f7fbf80,0x3f51bf42be163d49,
0xbf7f3f7c3f22bf0e,0xbcc93dfb3f3ebf4e,0xbf773f6f3ef1bec4,0xbe603ea13f5cbf67,0xbf653f583e95be48,0xbecf3efc3f71bf78,0xbf4a3f393dc98000,0xbf133f273f7dbf80,
0x3f803f80,0xbf80bf80,0x3f803f80,0xbf80bf80,0x3f803f80,0xbf80bf80,0x3f803f80,0xbf80bf80,
0xbf80bf8080008000,0x3f803f8080008000,0xbf80bf8080008000,0x3f803f8080008000,0xbf80bf8080008000,0x3f803f8080008000,0xbf80bf8080008000,0x3f803f8080008000,
0x3f653f58bef1bf0e,0xbf6abf5f3edb3f04,0x3f4a3f39bf22bf35,0xbf51bf423f183f2c,0x3f7f3f7cbdc9be48,0xbf80bf7e3d493e16,0x3f773f6fbe95bec4,0xbf7abf733e793eac,
0x3ee63f093f623f55,0xbecfbefcbf67bf5c,0x3f1d3f313f463f35,0xbf13bf27bf4ebf3e,0x3d973e2f3f7f3f7b,0xbcc9bdfbbf80bf7d,0x3e893eb83f753f6d,0xbe60bea1bf78bf71,
0xbf04bf2cbf55bf35,0x3edb3f183f623f46,0xbe16beacbf7bbf6d,0x3d493e793f7f3f75,0xbf78bf80be480000,0x3f713f7d3e953dc9,0xbf4ebf67bf0ebec4,0x3f3e3f5c3f223ef1,
0x3f5c3f3ebf0ebf35,0xbf67bf4e3ef13f22,0x3f7d3f71be48bec4,0xbf80bf783dc93e95,0x3e793d49bf7bbf80,0xbeacbe163f753f7f,0x3f183edbbf55bf6d,0xbf2cbf043f463f62,
0xbf7abf5f3e953f0e,0x3f7f3f6fbe16bedb,0xbf31bee63f463f6d,0x3f4a3f13bf2cbf5c,0xbe2f3dfb3f7f3f7b,0x3ea13cc9bf78bf80,0x3ecf3f273f623f35,0xbe89bf09bf71bf4e,
0xbe60befcbf75bf55,0x3d973eb83f7d3f67,0xbf39bf65bf22bec4,0x3f1d3f513f3e3f04,0xbf7cbf7ebdc93e48,0x3f733f803e79bd49,0xbf6abf423ef13f35,0x3f773f58beacbf18,
0x3ef13dc9bf6dbf80,0xbf22be953f553f7b,0x3f753f46bec4bf35,0xbf7fbf623e483f0e,0x3f623f7f3ec40000,0xbf46bf75bf0ebe48,0x3e953f223f6d3f35,0xbdc9bef1bf7bbf55,
0x3f623f7f3ec48000,0xbf46bf75bf0ebe48,0x3e953f223f6d3f35,0xbdc9bef1bf7bbf55,0xbef1bdc93f6d3f80,0x3f223e95bf55bf7b,0xbf75bf463ec43f35,0x3f7f3f62be48bf0e,
0xbf31bf73bf22be48,0x3efc3f583f4e3edb,0xbf7cbf4a3e953f35,0x3f7f3f6abd49bf04,0x3f6f3f27bef1bf55,0xbf7ebf513e793f2c,0x3e60be89bf7fbf6d,0xbee63cc93f713f7d,
0x3f393ea1bf46bf7b,0xbf5fbf093f183f67,0xbe2fbf1dbf75bf35,0xbd973ecf3f803f5c,0x3eb83f423f623f0e,0xbdfbbf13bf78bf3e,0x3f7a3f773dc9bec4,0xbf65bf80beac3e16,
0xbf80bf4e3e483f35,0x3f783f713dc9bef1,0xbedbbf5cbf55bec4,0x3e163f2c3f753f22,0x3f3e3f7d3f0e0000,0xbf04bf67bf46be95,0xbeac3e793f7b3f6d,0x3f183d49bf62bf7f,
0xbd49bf18bf7bbf35,0xbe793eac3f7f3f62,0x3f673f04bf0ebf6d,0xbf7dbf3e3e953f46,0xbf2cbe163f553f80,0x3f5c3edbbf22bf75,0xbf71bf78be483ec4,0x3f4e3f803ef1bdc9,
0xbf5fbeb83f223f7b,0x3f7c3f27beacbf5c,0x3ea13f583f623ec4,0x3cc9bf1dbf7dbf2c,0x3f7e3f31be95bf55,0xbf7abf65bd493f18,0x3d97bf13bf7fbf35,0xbecf3e893f783f67,
0xbefcbf6fbf46be48,0x3e2f3f423f713f04,0xbf73bf093ef13f6d,0x3f803f4abe16bf3e,0x3dfb3f393f753f0e,0x3e60bee6bf80bf4e,0x3f7f3f51bdc9bf35,0xbf6abf77be793edb,
0xbf55be483f353f80,0x3f7b3f0ebec4bf6d,0xbf0ebf7bbf350000,0x3e483f553f6d3ec4,0x3f553e48bf35bf80,0xbf7bbf0e3ec43f6d,0x3f0e3f7b3f350000,0xbe48bf55bf6dbec4,
0xbf0ebf7bbf358000,0x3e483f553f6d3ec4,0x3f553e48bf35bf80,0xbf7bbf0e3ec43f6d,0x3f0e3f7b3f358000,0xbe48bf55bf6dbec4,0xbf55be483f353f80,0x3f7b3f0ebec4bf6d,
0xbefc3eb83f753f55,0x3f513d97bf3ebf7d,0x3f733f583dc9bf35,0xbf39bf7ebf043eac,0x3f4a3cc9bf46bf7b,0xbf7abee63edb3f78,0xbf42bf7cbef13ec4,0x3ecf3f773f4e3d49,
0xbf5fbf6fbe953f0e,0x3f133f7f3f2cbe16,0xbea13f093f7f3f35,0x3f31bdfbbf5cbf71,0x3f1d3f803f22be48,0xbe60bf65bf67be79,0x3f27be2fbf62bf6d,0xbf6abe893f183f80,
0xbedb3f043f7b3f35,0x3f4ebd49bf46bf75,0xbf2cbf7dbf0e3ec4,0x3e793f713f623dc9,0xbeacbf78bf550000,0xbe163f3e3f7f3ef1,0x3f803f18be48bf6d,0xbf5cbf67be953f22,
0xbf67bf5cbe483f35,0x3f183f803f22be95,0x3f3ebe16bf55bf6d,0xbf78beac3ef13f7f,0x3f713e79bf0ebf80,0xbf7dbf2c3dc93f62,0xbd493f4e3f7b3ec4,0x3f04bedbbf75bf46,
0xbf313ea13f623f55,0x3f773e60bf04bf80,0x3f7c3f1dbdc9bf6d,0xbf42bf6fbedb3f18,0xbecfbf7fbf463e48,0xbdfb3f513f7d3eac,0xbf093efc3f753f35,0x3f653cc9bf2cbf78,
0xbf39bf73bef13f0e,0x3e893f7a3f5cbd49,0xbe2f3f4a3f7f3ec4,0x3f27beb8bf67bf4e,0x3f6a3d97bf22bf7b,0xbf7ebf133e163f71,0xbf58bf5fbe953f35,0x3ee63f803f3ebe79,
0x3f7f3e95bec4bf80,0xbf62bf46be483f55,0xbf223ef13f6d3f35,0x3f753dc9bf0ebf7b,0xbdc9bf75bf6d0000,0xbef13f223f7b3f0e,0x3f463f623ec4bf35,0xbe95bf7fbf553e48,
0x3dc93f753f6d8000,0x3ef1bf22bf7bbf0e,0xbf46bf62bec43f35,0x3e953f7f3f55be48,0x3f7f3e95bec4bf80,0xbf62bf46be483f55,0xbf223ef13f6d3f35,0x3f753dc9bf0ebf7b,
0x3f7a3efcbdc9bf7b,0xbf27bf6abf043f2c,0xbf31bf65bef13f35,0x3dfb3f7c3f67be16,0x3f13bf1dbf75bf0e,0xbf733cc93f183f71,0xbf6f3d973f223f6d,0x3f773f09bd49bf78,
0xbe603f5f3f7f3e48,0x3f42becfbf5cbf3e,0x3f39bee6bf62bf35,0xbf7ebe2f3edb3f7d,0x3f513f4a3e95bf55,0xbea1bf80bf4e3eac,0xbeb8bf7fbf463ec4,0xbe893f583f803e79,
0x3f183f673f0ebf35,0x3d49bf78bf753dc9,0xbf5cbf2cbe483f6d,0x3eac3f7d3f46bef1,0xbe163f713f7b0000,0x3f3ebf04bf62bf22,0xbe79bf80bf553ec4,0xbedb3f4e3f7f3e95,
0xbf4e3edb3f553f35,0x3f803e79be95bf7f,0x3f04bf3ebf7bbec4,0xbf713e163f223f62,0xbf7dbeac3e483f80,0x3f2c3f5c3ef1bf46,0x3f78bd49bf0ebf6d,0xbf67bf18bdc93f75,
0xbee63f583f7f3e48,0x3f6fbe89bf2cbf4e,0x3f1dbf39bf75bec4,0xbf7c3d973f043f67,0xbf423f133f623f0e,0x3f803dfbbeacbf78,0x3f5fbecfbf46bf35,0xbf7abea13e163f80,
0xbf65bf09bdc93f7b,0x3eb83f773f3ebf18,0x3f4a3f313e95bf6d,0xbe2fbf7fbf5c3edb,0xbf27bf51bef13f55,0xbcc93f7e3f71be79,0x3efc3f6a3f22bf35,0x3e60bf73bf7d3d49,
0xbf6dbec400003f80,0x3ec43f6d3f35bf35,0x3f6d3ec40000bf80,0xbec4bf6dbf353f35,0xbf6dbec400003f80,0x3ec43f6d3f35bf35,0x3f6d3ec40000bf80,0xbec4bf6dbf353f35,
0x3ec4bf6dbf808000,0xbf6d3ec43f353f35,0xbec43f6d3f808000,0x3f6dbec4bf35bf35,0x3ec4bf6dbf808000,0xbf6d3ec43f353f35,0xbec43f6d3f808000,0x3f6dbec4bf35bf35,
0xbd97bf7cbf623f0e,0xbf313f4a3f713e79,0x3e893f6f3f46bf35,0x3f09bf65bf7dbd49,0x3ea1bf7abf7f3e48,0xbf6a3efc3f3e3f18,0xbdfb3f803f75bec4,0x3f51bf27bf5cbedb,
0x3f7fbe2fbef1bf55,0xbf39bf1dbeac3f78,0xbf773eb83f223f35,0x3f583ee63e16bf80,0x3f733e60bdc9bf7b,0xbecfbf5fbf2c3f4e,0xbf7ebcc93e953f6d,0x3f133f423f04bf67,
0x3f7dbeacbf0ebf35,0xbf3ebf04be953f7f,0xbf78bd493e483f6d,0x3edb3f4e3f22bf62,0x3f18bf67bf7b0000,0xbf803e793ef13f46,0xbf5c3f2c3f553ec4,0x3f713e16bdc9bf75,
0x3e163f713f55bf35,0x3f2cbf5cbf75bdc9,0x3e79bf80bf7b3ec4,0xbf673f183f463ef1,0x3f4e3edb3e48bf80,0xbd49bf78bf623f22,0xbf04bf3ebf0e3f6d,0xbeac3f7d3f7fbe95,
0xbe2f3f7e3f75bf0e,0x3f65bf31bf4ebeac,0xbecfbf42bf223f6d,0xbefc3f7a3f80be79,0x3f583e893dc9bf7b,0xbd97bf6fbf5c3f3e,0xbf803ea13ef13f35,0x3f1d3f133edbbf7d,
0xbf7c3dfb3e953f55,0x3ee63f393f18bf71,0x3f6abf27bf46bec4,0xbf5fbe60bd493f78,0xbf093f773f7fbe48,0x3f7fbeb8bf04bf2c,0xbcc9bf73bf623f35,0xbf4a3f513f673e16,
0x3f223ef13ec4bf80,0x3e95bf7fbf7b3f0e,0x3dc9bf75bf6d3f35,0xbf623f463f553e48,0xbf463f623f6d0000,0x3f75bdc9be48bf55,0x3f7fbe95bec4bf35,0xbef1bf22bf0e3f7b,
0xbf463f623f6d8000,0x3f75bdc9be48bf55,0x3f7fbe95bec4bf35,0xbef1bf22bf0e3f7b,0xbf22bef1bec43f80,0xbe953f7f3f7bbf0e,0xbdc93f753f6dbf35,0x3f62bf46bf55be48,
0xbf6f3f423f463e48,0x3f4a3e2f3e16bf71,0x3e60bf77bf753f35,0xbf733f393f3e3e79,0x3cc9bf65bf623f55,0xbf5f3f583f5c3d49,0x3f513dfb3dc9bf6d,0x3d97bf6abf673f4e,
0xbeb8bf27bf223f7b,0xbf1d3f7c3f7dbeac,0x3f7abe89be95bf35,0xbea1bf31bf2c3f78,0x3f80bee6bef1bf0e,0xbefcbf09bf043f80,0xbf133f7e3f7fbec4,0x3f7fbecfbedbbf18,
0x3eacbf78bf7b3f35,0xbf7d3f2c3f223e95,0xbf803f183f0e3ec4,0x3f043edb3ef1bf7f,0xbf673f5c3f550000,0x3f4e3d493dc9bf62,0x3f3e3e163e48bf6d,0x3e79bf71bf753f46,
0x3f71be79be48bf35,0xbe16bf3ebf463f75,0xbd49bf4ebf553f6d,0xbf5c3f673f62bdc9,0xbedbbf04bf0e3f80,0xbf183f803f7fbef1,0xbf2c3f7d3f7bbec4,0x3f78beacbe95bf22,
0x3dfb3f313f46bf7b,0x3f58bf73bf673e79,0xbf7f3f133ef13ec4,0x3eb83efc3f18bf80,0x3e89bf6abf753f55,0xbf7c3f423f2c3e16,0x3f65be60bdc9bf35,0x3cc9bf4abf5c3f71,
0xbf7e3f393f223e48,0x3f093ea13edbbf78,0x3d97bf51bf623f6d,0xbf6f3f5f3f4ebd49,0x3f77becfbe95bf0e,0xbe2fbf27bf3e3f7d,0xbee63f7a3f7fbf35,0x3f80bf1dbf04beac,
0xbe48bf0ebf353f80,0xbf553f7b3f6dbec4,0xbf7b3f553f350000,0x3f0e3e483ec4bf6d,0x3e483f0e3f35bf80,0x3f55bf7bbf6d3ec4,0x3f7bbf55bf350000,0xbf0ebe48bec43f6d,
0x3f7bbf55bf358000,0xbf0ebe48bec43f6d,0xbe48bf0ebf353f80,0xbf553f7b3f6dbec4,0xbf7b3f553f358000,0x3f0e3e483ec4bf6d,0x3e483f0e3f35bf80,0x3f55bf7bbf6d3ec4,
0x3f1d3cc93e95bf55,0x3f09bf73bf803f4e,0xbf273f7c3f7fbf35,0x3f6fbefcbe79bedb,0xbe89becfbf223f7b,0xbf513f7f3f71bf04,0x3f65bf7abf623ec4,0xbf393dfbbe163f3e,
0xbf4a3f803f75bf0e,0x3f58bea1bd49bf18,0xbf423e2fbdc93f35,0xbeb83f5f3f78bf67,0x3f77bf6abf463e48,0xbf13bd97beac3f5c,0x3ee63e603ef1bf6d,0x3f31bf7ebf7d3f2c,
0xbf2c3e16be483f35,0xbf043f673f7fbf62,0xbf713f783f55bec4,0x3f18bd493e95bf46,0x3f80bf4ebf0e0000,0xbe79beacbf223f75,0x3edbbf5cbf7b3f6d,0xbf7d3f3e3ef13dc9,
0x3f3ebf7dbf7b3f35,0xbf5c3edb3dc93ef1,0xbeacbe79bf0e3f6d,0xbf4e3f803f75bf22,0xbd493f183f55bf80,0x3f78bf71bf463e95,0x3f67bf04be48bec4,0x3e16bf2cbf623f7f,
0x3ecf3d973ef1bf55,0x3f4abf7cbf783f3e,0xbf093f5f3f7fbf6d,0x3f73bf31beacbe16,0xbf803f653f22be48,0x3e893e603f18bf67,0xbf133dfbbe953f35,0xbf273f6f3f80bf5c,
0xbf6a3f7f3f62bf0e,0x3f1dbe2f3e79bf2c,0xbf583efc3dc93ec4,0xbea13f393f71bf7d,0xbcc9bee6bf463f7b,0xbf773f7a3f4ebedb,0x3f51bf7ebf753f35,0xbf423eb8bd493f04,
0xbe953f223f6dbf80,0x3f7fbf62bf0e3e48,0x3ef1bdc93ec4bf35,0x3f46bf75bf7b3f55,0x3f75bf46bec40000,0x3dc9bef1bf553f7b,0x3f62bf7fbf6d3f35,0xbf223e95be483f0e,
0xbf753f463ec48000,0xbdc93ef13f55bf7b,0xbf623f7f3f6dbf35,0x3f22be953e48bf0e,0xbe953f223f6dbf80,0x3f7fbf62bf0e3e48,0x3ef1bdc93ec4bf35,0x3f46bf75bf7b3f55,
0x3f13bf4abf7f3f7b,0xbf653f393e793d49,0x3f6fbf7fbf623f35,0xbefc3e60beac3f18,0xbf093e89be953f0e,0xbf423f6a3f7dbf67,0x3cc9bea1bf463f6d,0xbf7e3f7c3f3ebf04,
0x3f51bf1dbdc9be48,0x3ee6bf31bf783f80,0x3eb8bd973ef1bf35,0x3f5fbf7abf713f4e,0x3f58bf77bf753f55,0xbf273ecfbe163edb,0x3f80bf73bf223ec4,0xbdfbbe2fbf2c3f5c,
0xbf783f803f55bf35,0x3eacbe163ef1bf22,0xbf4e3f673f7bbf6d,0x3f2cbf043dc9be95,0xbf5c3f3e3e480000,0xbedb3f183f75bf7f,0xbf7d3f713f0ebec4,0xbd493e793f46bf62,
0xbe793d49bf0e3f35,0xbf713f7d3f62bf46,0xbf183edbbe483ec4,0xbf3e3f5c3f7fbf75,0x3f04bf2cbf7b3f80,0xbf673f4e3e95bdc9,0x3e16beacbf553f6d,0xbf803f783f22bef1,
0x3f27bf133dc9be48,0x3f39bf4abf803f7d,0x3efcbecf3e95bec4,0x3f58bf65bf783f71,0x3ea1be603ef1bf0e,0x3f6fbf77bf673f5c,0x3dfbbcc93f22bf35,0x3f7cbf7fbf4e3f3e,
0xbf423f513f7fbf7b,0x3f31bf1d3d49be16,0xbf5f3f6a3f75bf6d,0x3f09bee63e79beac,0xbf733f7a3f62bf55,0x3eb8be893edbbf04,0xbf7e3f803f46bf35,0x3e2fbd973f18bf2c,
0x3f803f80,0xbf80bf80,0x3f803f80,0xbf80bf80,0x3f803f80,0xbf80bf80,0x3f803f80,0xbf80bf80,
0xbf80bf8080008000,0x3f803f8080008000,0xbf80bf8080008000,0x3f803f8080008000,0xbf80bf8080008000,0x3f803f8080008000,0xbf80bf8080008000,0x3f803f8080008000,
0x3f733f7a3e953e48,0xbf6fbf77beacbe79,0x3f7e3f803dc90000,0xbf7cbf7fbe16bd49,0x3f423f513f223f0e,0xbf39bf4abf2cbf18,0x3f5f3f6a3ef13ec4,0xbf58bf65bf04bedb,
0xbea1be603f753f7b,0x3eb83e89bf71bf78,0xbdfbbcc93f7f3f80,0x3e2f3d97bf7dbf80,0xbf27bf133f463f55,0x3f313f1dbf3ebf4e,0xbefcbecf3f623f6d,0x3f093ee6bf5cbf67,
0x3f5c3f3ebf0ebf35,0xbf67bf4e3ef13f22,0x3f7d3f71be48bec4,0xbf80bf783dc93e95,0x3e793d49bf7bbf80,0xbeacbe163f753f7f,0x3f183edbbf55bf6d,0xbf2cbf043f463f62,
0x3f043f2c3f553f35,0xbedbbf18bf62bf46,0x3e163eac3f7b3f6d,0xbd49be79bf7fbf75,0x3f783f803e488000,0xbf71bf7dbe95bdc9,0x3f4e3f673f0e3ec4,0xbf3ebf5cbf22bef1,
0x3f093e89bf62bf7b,0xbf27becf3f4e3f71,0xbcc9bea1bf7fbf6d,0xbdfb3e2f3f803f78,0xbf13bf4abf46bf0e,0x3ee63f313f5c3f2c,0xbf6fbf7fbe950000,0x3f5f3f7a3edb3e16,
0x3f583f773ef13e48,0xbf42bf6abf18beac,0x3f803f73bdc9bec4,0xbf7ebf7cbd493e79,0x3f513f1dbf22bf55,0xbf65bf393f043f3e,0x3eb83d97bf75bf80,0xbefcbe603f673f7d,
0xbef1bdc93f6d3f80,0x3f223e95bf55bf7b,0xbf75bf463ec43f35,0x3f7f3f62be48bf0e,0xbf62bf7fbec40000,0x3f463f753f0e3e48,0xbe95bf22bf6dbf35,0x3dc93ef13f7b3f55,
0xbf62bf7fbec48000,0x3f463f753f0e3e48,0xbe95bf22bf6dbf35,0x3dc93ef13f7b3f55,0x3ef13dc9bf6dbf80,0xbf22be953f553f7b,0x3f753f46bec4bf35,0xbf7fbf623e483f0e,
0xbcc93ee63f7f3f55,0x3e89be60bf7dbf71,0x3f513f7e3ef10000,0xbf27bf6fbf2cbe79,0xbf6abf7fbe953e48,0x3f4a3f7c3f043d49,0xbf58befc3f223f6d,0x3f733f31bedbbf4e,
0xbf80bf653dc93f0e,0x3f773f7a3e16beac,0xbf13bdfb3f623f80,0x3f423eb8bf3ebf78,0x3ecfbd97bf75bf7b,0xbf1dbe2f3f5c3f80,0xbf09bf5fbf46bec4,0x3ea13f393f673f18,
0x3d493f183f7b3f35,0x3e79beacbf7fbf62,0xbf67bf043f0e3f6d,0x3f7d3f3ebe95bf46,0x3f2c3e16bf55bf80,0xbf5cbedb3f223f75,0x3f713f783e48bec4,0xbf4ebf80bef13dc9,
0xbf80bf4e3e483f35,0x3f783f713dc9bef1,0xbedbbf5cbf55bec4,0x3e163f2c3f753f22,0x3f3e3f7d3f0e8000,0xbf04bf67bf46be95,0xbeac3e793f7b3f6d,0x3f183d49bf62bf7f,
0xbe893ecf3f7f3f55,0x3f13bd97bf67bf78,0x3f653f7a3e95bec4,0xbf31bf7ebf183d49,0x3f1dbcc9bf62bf7b,0xbf58bea13f2c3f7d,0xbf27bf7cbf220000,0x3eb83f5f3f5c3eac,
0xbf77bf6abdc93f0e,0x3f513f7f3edbbe79,0xbee63e603f753f6d,0x3f393dfbbf4ebf80,0x3f4a3f803ef1be48,0xbf09bf73bf3ebe16,0x3f423e2fbf46bf80,0xbf6fbefc3f043f71,
0xbf55be483f353f80,0x3f7b3f0ebec4bf6d,0xbf0ebf7bbf350000,0x3e483f553f6d3ec4,0x3f553e48bf35bf80,0xbf7bbf0e3ec43f6d,0x3f0e3f7b3f350000,0xbe48bf55bf6dbec4,
0xbf0ebf7bbf358000,0x3e483f553f6d3ec4,0x3f553e48bf35bf80,0xbf7bbf0e3ec43f6d,0x3f0e3f7b3f358000,0xbe48bf55bf6dbec4,0xbf55be483f353f80,0x3f7b3f0ebec4bf6d,
0xbf77becf3ef13f7b,0x3f7c3f42bd49bf4e,0x3ee63f7a3f460000,0xbcc9bf4abf78bedb,0x3f7e3f39bdc9bf55,0xbf58bf73beac3f04,0xbd97bf51bf75bec4,0xbeb83efc3f7d3f3e,
0xbe89bf6abf62be48,0xbe2f3f273f803f18,0xbf65be603f223f80,0x3f803f1dbe79bf67,0xbdfb3f313f7f3f0e,0x3f09bea1bf71bf5c,0x3f7f3f13be95bf6d,0xbf6fbf5fbe163f2c,
0xbf67bf5cbe483f35,0x3f183f803f22be95,0x3f3ebe16bf55bf6d,0xbf78beac3ef13f7f,0x3f713e79bf0ebf80,0xbf7dbf2c3dc93f62,0xbd493f4e3f7b3ec4,0x3f04bedbbf75bf46,
0x3edbbf04bf7bbf35,0xbf4e3d493f463f75,0x3f2c3f7d3f0ebec4,0xbe79bf71bf62bdc9,0x3eac3f783f558000,0x3e16bf3ebf7fbef1,0xbf80bf183e483f6d,0x3f5c3f673e95bf22,
0xbcc9bf65bf75be48,0xbefc3f093f783f2c,0xbf513dfb3f463f6d,0x3f7f3ecfbeacbf7d,0x3f6f3f423dc9bf55,0xbf1dbf7cbf183edb,0xbe60bf77bf620000,0xbea13f313f803f04,
0x3f803ee6be95bf7b,0xbf5fbf58be793f3e,0xbf13bf7ebf223ec4,0x3d973f6a3f713e16,0xbeb83f273f7f3f0e,0x3f4abe2fbf4ebf67,0x3f7a3e89bef1bf80,0xbf73bf39bd493f5c,
0xbf7fbe953ec43f80,0x3f623f463e48bf55,0x3f22bef1bf6dbf35,0xbf75bdc93f0e3f7b,0x3dc93f753f6d0000,0x3ef1bf22bf7bbf0e,0xbf46bf62bec43f35,0x3e953f7f3f55be48,
0xbdc9bf75bf6d8000,0xbef13f223f7b3f0e,0x3f463f623ec4bf35,0xbe95bf7fbf553e48,0xbf7fbe953ec43f80,0x3f623f463e48bf55,0x3f22bef1bf6dbf35,0xbf75bdc93f0e3f7b,
0xbf09bf77bf223f0e,0xbd973f6f3f783d49,0xbcc93f733f750000,0x3f1dbf13bf71bf18,0xbf7cbdfb3ef13f7b,0x3f653f313e16bf67,0x3f6a3f273dc9bf6d,0xbefcbf7abf2c3f04,
0x3f58be89bf46bf55,0xbf7fbeb83e793f80,0xbf80bea13e953f80,0x3f4a3f513eacbf4e,0xbe2fbf7ebf623e48,0xbee63f393f7d3edb,0xbecf3f423f7f3ec4,0x3f5fbe60bf3ebf5c,
0x3f4ebedbbf55bf35,0xbf80be793e953f7f,0xbf043f3e3f7b3ec4,0x3f71be16bf22bf62,0x3f7d3eacbe48bf80,0xbf2cbf5cbef13f46,0xbf783d493f0e3f6d,0x3f673f183dc9bf75,
0x3f183f673f0ebf35,0x3d49bf78bf753dc9,0xbf5cbf2cbe483f6d,0x3eac3f7d3f46bef1,0xbe163f713f7b8000,0x3f3ebf04bf62bf22,0xbe79bf80bf553ec4,0xbedb3f4e3f7f3e95,
0x3ea13f7a3f46bf0e,0x3ecfbf5fbf80be16,0xbdfbbf80bf623ec4,0xbf133f423f783eac,0xbd973f7c3f75be48,0x3f39bf1dbf67bf04,0x3e89bf6fbf7f0000,0xbf583ee63f4e3f2c,
0xbf733e603f223f55,0x3f6a3efc3d49bf7d,0x3f7ebcc9bef1bf6d,0xbf51bf27be793f71,0xbf7fbe2f3e953f7b,0x3f313f4a3edbbf5c,0x3f773eb8bdc9bf80,0xbf09bf65bf183f3e,
0xbf6dbec400003f80,0x3ec43f6d3f35bf35,0x3f6d3ec40000bf80,0xbec4bf6dbf353f35,0xbf6dbec400003f80,0x3ec43f6d3f35bf35,0x3f6d3ec40000bf80,0xbec4bf6dbf353f35,
0x3ec4bf6dbf808000,0xbf6d3ec43f353f35,0xbec43f6d3f808000,0x3f6dbec4bf35bf35,0x3ec4bf6dbf808000,0xbf6d3ec43f353f35,0xbec43f6d3f808000,0x3f6dbec4bf35bf35,
0x3f27bf51bf75be48,0xbf803dfb3edb3f5c,0xbefc3f6a3f7f0000,0x3f7abea1bf18bf3e,0x3f65bf09bf46bf0e,0xbf6fbe893d493f7d,0xbf4a3f313f623ec4,0x3f7c3d97be79bf71,
0x3f423f133e95bf7b,0xbcc9bf7ebf673f04,0xbf5fbecfbdc93f80,0x3e603f733f4ebf2c,0x3ee63f583f22bf55,0x3eb8bf77bf803e16,0xbf1dbf39bef13f6d,0xbe2f3f7f3f78beac,
0x3e163f713f55bf35,0x3f2cbf5cbf75bdc9,0x3e79bf80bf7b3ec4,0xbf673f183f463ef1,0x3f4e3edb3e48bf80,0xbd49bf78bf623f22,0xbf04bf3ebf0e3f6d,0xbeac3f7d3f7fbe95,
0xbf7d3eac3f0e3f35,0x3f3e3f043e95bf7f,0x3f783d49be48bf6d,0xbedbbf4ebf223f62,0xbf183f673f7b8000,0x3f80be79bef1bf46,0x3f5cbf2cbf55bec4,0xbf71be163dc93f75,
0xbf13bf1dbef13f7b,0xbea13f803f7dbedb,0x3f6f3d97bdc9bf6d,0xbe89bf58bf3e3f5c,0xbf7a3efc3f223f0e,0x3f423ecf3e79bf80,0x3f31bf65bf750000,0xbf7e3e2f3eac3f4e,
0x3f51bf4abf62be48,0xbf73bcc93e163f67,0xbeb83f7f3f7fbec4,0x3f77bf09bf2cbf04,0xbe60bf5fbf463f55,0xbf273f6a3f78bd49,0x3f393ee63e95bf80,0x3dfbbf7cbf713f18,
0xbf22bef1bec43f80,0xbe953f7f3f7bbf0e,0xbdc93f753f6dbf35,0x3f62bf46bf55be48,0x3f46bf62bf6d0000,0xbf753dc93e483f55,0xbf7f3e953ec43f35,0x3ef13f223f0ebf7b,
0x3f46bf62bf6d8000,0xbf753dc93e483f55,0xbf7f3e953ec43f35,0x3ef13f223f0ebf7b,0x3f223ef13ec4bf80,0x3e95bf7fbf7b3f0e,0x3dc9bf75bf6d3f35,0xbf623f463f553e48,
0x3f6abd97bdc9bf55,0xbdfbbf51bf4e3f67,0xbf583f5f3f620000,0x3f65bcc9bd49bf5c,0xbf393f733f75be48,0x3f77be60be79bf3e,0xbe2fbf4abf463f6d,0xbf423f6f3f71be16,
0xbecf3f7f3f7fbf0e,0x3f7ebf13bf18bedb,0xbf09befcbef13f80,0xbee63f803f80bf04,0xbf31bea1be953f7b,0xbe893f7a3f78bf2c,0x3f7cbf1dbf22bec4,0xbf27beb8beac3f7d,
0xbf713e793e483f35,0x3e163f3e3f46bf75,0x3d493f4e3f55bf6d,0x3f5cbf67bf623dc9,0x3edb3f043f0ebf80,0x3f18bf80bf7f3ef1,0x3f2cbf7dbf7b3ec4,0xbf783eac3e953f22,
0x3eacbf78bf7b3f35,0xbf7d3f2c3f223e95,0xbf803f183f0e3ec4,0x3f043edb3ef1bf7f,0xbf673f5c3f558000,0x3f4e3d493dc9bf62,0x3f3e3e163e48bf6d,0x3e79bf71bf753f46,
0x3f4abcc93dc9bf55,0x3e60bf65bf713f5c,0xbf423f7c3f75bec4,0x3f6abe89be16bf2c,0xbefcbeb8bef13f7b,0xbf133f7f3f80bf18,0x3f73bf58bf460000,0xbf31bdfbbe793f67,
0xbf1d3f803f7fbf0e,0x3f7abee6beacbf04,0xbf27be2fbe953f6d,0xbecf3f773f7dbf3e,0x3f5fbf6fbf623e48,0xbf513d97bd493f4e,0x3ea13f093f22bf80,0x3f39bf7ebf783edb,
0xbe48bf0ebf353f80,0xbf553f7b3f6dbec4,0xbf7b3f553f350000,0x3f0e3e483ec4bf6d,0x3e483f0e3f35bf80,0x3f55bf7bbf6d3ec4,0x3f7bbf55bf350000,0xbf0ebe48bec43f6d,
0x3f7bbf55bf358000,0xbf0ebe48bec43f6d,0xbe48bf0ebf353f80,0xbf553f7b3f6dbec4,0xbf7b3f553f358000,0x3f0e3e483ec4bf6d,0x3e483f0e3f35bf80,0x3f55bf7bbf6d3ec4,
0xbdfb3f393f62bf7b,0x3f7abf65bf3e3e16,0xbf7f3f513f220000,0x3ecf3e893f04bf71,0x3efcbf6fbf7f3f55,0xbf7c3f273edb3e79,0x3f73bf09be95bec4,0xbcc9bf1dbf4e3f80,
0xbf7e3f313ef13e48,0x3e603ee63f2cbf7d,0xbd97bf13bf463f80,0xbf6a3f773f5cbeac,0x3f5fbeb8bdc9bf0e,0x3e2fbf42bf673f78,0xbea13f583f75bf6d,0x3f80bf4abf18bd49,
0x3f3ebf7dbf7b3f35,0xbf5c3edb3dc93ef1,0xbeacbe79bf0e3f6d,0xbf4e3f803f75bf22,0xbd493f183f55bf80,0x3f78bf71bf463e95,0x3f67bf04be48bec4,0x3e16bf2cbf623f7f,
0x3f2cbe163e48bf35,0x3f04bf67bf7f3f62,0x3f71bf78bf553ec4,0xbf183d49be953f46,0xbf803f4e3f0e8000,0x3e793eac3f22bf75,0xbedb3f5c3f7bbf6d,0x3f7dbf3ebef1bdc9,
0xbf6f3f273e953e48,0xbdfb3f133f5cbf80,0xbe60be89bf223f6d,0xbf653f803f67bf18,0x3f31bf73bf7f3f55,0xbf5f3f093e163eac,0x3f7cbf4abef10000,0xbd97becfbf3e3f78,
0x3eb8bf42bf753f7b,0xbf7e3f513f04bd49,0x3f7abf77bf463ec4,0xbee6bcc9bedb3f4e,0x3f39bea13dc9bf0e,0x3efcbf58bf7d3f71,0xbe2f3f1d3f62bf80,0x3f7fbf6abf2c3e79,
0x3e95bf22bf6d3f80,0xbf7f3f623f0ebe48,0xbef13dc9bec43f35,0xbf463f753f7bbf55,0xbf753f463ec40000,0xbdc93ef13f55bf7b,0xbf623f7f3f6dbf35,0x3f22be953e48bf0e,
0x3f75bf46bec48000,0x3dc9bef1bf553f7b,0x3f62bf7fbf6d3f35,0xbf223e95be483f0e,0x3e95bf22bf6d3f80,0xbf7f3f623f0ebe48,0xbef13dc9bec43f35,0xbf463f753f7bbf55,
0xbf7c3f7e3f46bf0e,0x3ea1bcc93f04bf3e,0xbf6a3f423e950000,0xbe893f093f67bf7d,0xbe603efc3f62bf7b,0x3f7fbf6fbf183eac,0xbf393f653f7fbf6d,0x3f4abf13bd49be79,
0xbe2fbdfbbf223f55,0xbf733f803f5cbf2c,0x3ecfbf27bf753f80,0xbf773f583edbbe16,0xbf7a3f5f3ef1be48,0xbd973eb83f4ebf71,0xbf313ee6bdc93ec4,0xbf1d3f513f80bf78,
0x3e79bd493f0ebf35,0x3f71bf7dbf623f46,0x3f18bedb3e48bec4,0x3f3ebf5cbf7f3f75,0xbf043f2c3f7bbf80,0x3f67bf4ebe953dc9,0xbe163eac3f55bf6d,0x3f80bf78bf223ef1,
0xbf783f803f55bf35,0x3eacbe163ef1bf22,0xbf4e3f673f7bbf6d,0x3f2cbf043dc9be95,0xbf5c3f3e3e488000,0xbedb3f183f75bf7f,0xbf7d3f713f0ebec4,0xbd493e793f46bf62,
0x3f7fbf7cbf223f0e,0x3cc9bdfbbf3e3f4e,0x3f77bf6fbef13ec4,0x3e60bea1bf5c3f67,0x3f65bf58be953e48,0x3ecfbefcbf713f78,0x3f4abf39bdc90000,0x3f13bf27bf7d3f80,
0xbd973e2f3f46bf55,0x3f80bf7ebf2c3f18,0xbe893eb83f62bf6d,0x3f7abf73bf043edb,0xbee63f093f75bf7b,0x3f6abf5fbeac3e79,0xbf1d3f313f7fbf80,0x3f51bf42be163d49,
0x3f803f80,0xbf80bf80,0x3f803f80,0xbf80bf80,0x3f803f80,0xbf80bf80,0x3f803f80,0xbf80bf80,
0xbf80bf8080008000,0x3f803f8080008000,0xbf80bf8080008000,0x3f803f8080008000,0xbf80bf8080008000,0x3f803f8080008000,0xbf80bf8080008000,0x3f803f8080008000,
0x3ee63f093f623f55,0xbecfbefcbf67bf5c,0x3f1d3f313f463f35,0xbf13bf27bf4ebf3e,0x3d973e2f3f7f3f7b,0xbcc9bdfbbf80bf7d,0x3e893eb83f753f6d,0xbe60bea1bf78bf71,
0xbf65bf583ef13f0e,0x3f6a3f5fbedbbf04,0xbf4abf393f223f35,0x3f513f42bf18bf2c,0xbf7fbf7c3dc93e48,0x3f803f7ebd49be16,0xbf77bf6f3e953ec4,0x3f7a3f73be79beac,
0x3f043f2c3f553f35,0xbedbbf18bf62bf46,0x3e163eac3f7b3f6d,0xbd49be79bf7fbf75,0x3f783f803e480000,0xbf71bf7dbe95bdc9,0x3f4e3f673f0e3ec4,0xbf3ebf5cbf22bef1,
0xbf5cbf3e3f0e3f35,0x3f673f4ebef1bf22,0xbf7dbf713e483ec4,0x3f803f78bdc9be95,0xbe79bd493f7b3f80,0x3eac3e16bf75bf7f,0xbf18bedb3f553f6d,0x3f2c3f04bf46bf62,
0x3e603efc3f753f55,0xbd97beb8bf7dbf67,0x3f393f653f223ec4,0xbf1dbf51bf3ebf04,0x3f7c3f7e3dc9be48,0xbf73bf80be793d49,0x3f6a3f42bef1bf35,0xbf77bf583eac3f18,
0xbf7abf5f3e953f0e,0x3f7f3f6fbe16bedb,0xbf31bee63f463f6d,0x3f4a3f13bf2cbf5c,0xbe2f3dfb3f7f3f7b,0x3ea13cc9bf78bf80,0x3ecf3f273f623f35,0xbe89bf09bf71bf4e,
0x3ef13dc9bf6dbf80,0xbf22be953f553f7b,0x3f753f46bec4bf35,0xbf7fbf623e483f0e,0x3f623f7f3ec40000,0xbf46bf75bf0ebe48,0x3e953f223f6d3f35,0xbdc9bef1bf7bbf55,
0x3f623f7f3ec48000,0xbf46bf75bf0ebe48,0x3e953f223f6d3f35,0xbdc9bef1bf7bbf55,0xbef1bdc93f6d3f80,0x3f223e95bf55bf7b,0xbf75bf463ec43f35,0x3f7f3f62be48bf0e,
0x3f393ea1bf46bf7b,0xbf5fbf093f183f67,0xbe2fbf1dbf75bf35,0xbd973ecf3f803f5c,0x3eb83f423f623f0e,0xbdfbbf13bf78bf3e,0x3f7a3f773dc9bec4,0xbf65bf80beac3e16,
0x3f313f733f223e48,0xbefcbf58bf4ebedb,0x3f7c3f4abe95bf35,0xbf7fbf6a3d493f04,0xbf6fbf273ef13f55,0x3f7e3f51be79bf2c,0xbe603e893f7f3f6d,0x3ee6bcc9bf71bf7d,
0x3f803f4ebe48bf35,0xbf78bf71bdc93ef1,0x3edb3f5c3f553ec4,0xbe16bf2cbf75bf22,0xbf3ebf7dbf0e0000,0x3f043f673f463e95,0x3eacbe79bf7bbf6d,0xbf18bd493f623f7f,
0x3d493f183f7b3f35,0x3e79beacbf7fbf62,0xbf67bf043f0e3f6d,0x3f7d3f3ebe95bf46,0x3f2c3e16bf55bf80,0xbf5cbedb3f223f75,0x3f713f783e48bec4,0xbf4ebf80bef13dc9,
0x3efc3f6f3f463e48,0xbe2fbf42bf71bf04,0x3f733f09bef1bf6d,0xbf80bf4a3e163f3e,0xbdfbbf39bf75bf0e,0xbe603ee63f803f4e,0xbf7fbf513dc93f35,0x3f6a3f773e79bedb,
0xbf5fbeb83f223f7b,0x3f7c3f27beacbf5c,0x3ea13f583f623ec4,0x3cc9bf1dbf7dbf2c,0x3f7e3f31be95bf55,0xbf7abf65bd493f18,0x3d97bf13bf7fbf35,0xbecf3e893f783f67,
0xbf55be483f353f80,0x3f7b3f0ebec4bf6d,0xbf0ebf7bbf350000,0x3e483f553f6d3ec4,0x3f553e48bf35bf80,0xbf7bbf0e3ec43f6d,0x3f0e3f7b3f350000,0xbe48bf55bf6dbec4,
0xbf0ebf7bbf358000,0x3e483f553f6d3ec4,0x3f553e48bf35bf80,0xbf7bbf0e3ec43f6d,0x3f0e3f7b3f358000,0xbe48bf55bf6dbec4,0xbf55be483f353f80,0x3f7b3f0ebec4bf6d,
0xbf5fbf6fbe953f0e,0x3f133f7f3f2cbe16,0xbea13f093f7f3f35,0x3f31bdfbbf5cbf71,0x3f1d3f803f22be48,0xbe60bf65bf67be79,0x3f27be2fbf62bf6d,0xbf6abe893f183f80,
0x3efcbeb8bf75bf55,0xbf51bd973f3e3f7d,0xbf73bf58bdc93f35,0x3f393f7e3f04beac,0xbf4abcc93f463f7b,0x3f7a3ee6bedbbf78,0x3f423f7c3ef1bec4,0xbecfbf77bf4ebd49,
0x3edbbf04bf7bbf35,0xbf4e3d493f463f75,0x3f2c3f7d3f0ebec4,0xbe79bf71bf62bdc9,0x3eac3f783f550000,0x3e16bf3ebf7fbef1,0xbf80bf183e483f6d,0x3f5c3f673e95bf22,
0x3f673f5c3e48bf35,0xbf18bf80bf223e95,0xbf3e3e163f553f6d,0x3f783eacbef1bf7f,0xbf71be793f0e3f80,0x3f7d3f2cbdc9bf62,0x3d49bf4ebf7bbec4,0xbf043edb3f753f46,
0x3f393f733ef1bf0e,0xbe89bf7abf5c3d49,0x3e2fbf4abf7fbec4,0xbf273eb83f673f4e,0xbf6abd973f223f7b,0x3f7e3f13be16bf71,0x3f583f5f3e95bf35,0xbee6bf80bf3e3e79,
0xbf313ea13f623f55,0x3f773e60bf04bf80,0x3f7c3f1dbdc9bf6d,0xbf42bf6fbedb3f18,0xbecfbf7fbf463e48,0xbdfb3f513f7d3eac,0xbf093efc3f753f35,0x3f653cc9bf2cbf78,
0x3f7f3e95bec4bf80,0xbf62bf46be483f55,0xbf223ef13f6d3f35,0x3f753dc9bf0ebf7b,0xbdc9bf75bf6d0000,0xbef13f223f7b3f0e,0x3f463f623ec4bf35,0xbe95bf7fbf553e48,
0x3dc93f753f6d8000,0x3ef1bf22bf7bbf0e,0xbf46bf62bec43f35,0x3e953f7f3f55be48,0x3f7f3e95bec4bf80,0xbf62bf46be483f55,0xbf223ef13f6d3f35,0x3f753dc9bf0ebf7b,
0xbe603f5f3f7f3e48,0x3f42becfbf5cbf3e,0x3f39bee6bf62bf35,0xbf7ebe2f3edb3f7d,0x3f513f4a3e95bf55,0xbea1bf80bf4e3eac,0xbeb8bf7fbf463ec4,0xbe893f583f803e79,
0xbf7abefc3dc93f7b,0x3f273f6a3f04bf2c,0x3f313f653ef1bf35,0xbdfbbf7cbf673e16,0xbf133f1d3f753f0e,0x3f73bcc9bf18bf71,0x3f6fbd97bf22bf6d,0xbf77bf093d493f78,
0xbf18bf67bf0e3f35,0xbd493f783f75bdc9,0x3f5c3f2c3e48bf6d,0xbeacbf7dbf463ef1,0x3e16bf71bf7b0000,0xbf3e3f043f623f22,0x3e793f803f55bec4,0x3edbbf4ebf7fbe95,
0x3f4ebedbbf55bf35,0xbf80be793e953f7f,0xbf043f3e3f7b3ec4,0x3f71be16bf22bf62,0x3f7d3eacbe48bf80,0xbf2cbf5cbef13f46,0xbf783d493f0e3f6d,0x3f673f183dc9bf75,
0x3f653f093dc9bf7b,0xbeb8bf77bf3e3f18,0xbf4abf31be953f6d,0x3e2f3f7f3f5cbedb,0x3f273f513ef1bf55,0x3cc9bf7ebf713e79,0xbefcbf6abf223f35,0xbe603f733f7dbd49,
0xbee63f583f7f3e48,0x3f6fbe89bf2cbf4e,0x3f1dbf39bf75bec4,0xbf7c3d973f043f67,0xbf423f133f623f0e,0x3f803dfbbeacbf78,0x3f5fbecfbf46bf35,0xbf7abea13e163f80,
0xbf6dbec400003f80,0x3ec43f6d3f35bf35,0x3f6d3ec40000bf80,0xbec4bf6dbf353f35,0xbf6dbec400003f80,0x3ec43f6d3f35bf35,0x3f6d3ec40000bf80,0xbec4bf6dbf353f35,
0x3ec4bf6dbf808000,0xbf6d3ec43f353f35,0xbec43f6d3f808000,0x3f6dbec4bf35bf35,0x3ec4bf6dbf808000,0xbf6d3ec43f353f35,0xbec43f6d3f808000,0x3f6dbec4bf35bf35,
0x3f7fbe2fbef1bf55,0xbf39bf1dbeac3f78,0xbf773eb83f223f35,0x3f583ee63e16bf80,0x3f733e60bdc9bf7b,0xbecfbf5fbf2c3f4e,0xbf7ebcc93e953f6d,0x3f133f423f04bf67,
0x3d973f7c3f62bf0e,0x3f31bf4abf71be79,0xbe89bf6fbf463f35,0xbf093f653f7d3d49,0xbea13f7a3f7fbe48,0x3f6abefcbf3ebf18,0x3dfbbf80bf753ec4,0xbf513f273f5c3edb,
0xbf7d3eac3f0e3f35,0x3f3e3f043e95bf7f,0x3f783d49be48bf6d,0xbedbbf4ebf223f62,0xbf183f673f7b0000,0x3f80be79bef1bf46,0x3f5cbf2cbf55bec4,0xbf71be163dc93f75,
0xbe16bf71bf553f35,0xbf2c3f5c3f753dc9,0xbe793f803f7bbec4,0x3f67bf18bf46bef1,0xbf4ebedbbe483f80,0x3d493f783f62bf22,0x3f043f3e3f0ebf6d,0x3eacbf7dbf7f3e95,
0x3f7cbdfbbe95bf55,0xbee6bf39bf183f71,0xbf6a3f273f463ec4,0x3f5f3e603d49bf78,0x3f09bf77bf7f3e48,0xbf7f3eb83f043f2c,0x3cc93f733f62bf35,0x3f4abf51bf67be16,
0xbe2f3f7e3f75bf0e,0x3f65bf31bf4ebeac,0xbecfbf42bf223f6d,0xbefc3f7a3f80be79,0x3f583e893dc9bf7b,0xbd97bf6fbf5c3f3e,0xbf803ea13ef13f35,0x3f1d3f133edbbf7d,
0x3f223ef13ec4bf80,0x3e95bf7fbf7b3f0e,0x3dc9bf75bf6d3f35,0xbf623f463f553e48,0xbf463f623f6d0000,0x3f75bdc9be48bf55,0x3f7fbe95bec4bf35,0xbef1bf22bf0e3f7b,
0xbf463f623f6d8000,0x3f75bdc9be48bf55,0x3f7fbe95bec4bf35,0xbef1bf22bf0e3f7b,0xbf22bef1bec43f80,0xbe953f7f3f7bbf0e,0xbdc93f753f6dbf35,0x3f62bf46bf55be48,
0xbeb8bf27bf223f7b,0xbf1d3f7c3f7dbeac,0x3f7abe89be95bf35,0xbea1bf31bf2c3f78,0x3f80bee6bef1bf0e,0xbefcbf09bf043f80,0xbf133f7e3f7fbec4,0x3f7fbecfbedbbf18,
0x3f6fbf42bf46be48,0xbf4abe2fbe163f71,0xbe603f773f75bf35,0x3f73bf39bf3ebe79,0xbcc93f653f62bf55,0x3f5fbf58bf5cbd49,0xbf51bdfbbdc93f6d,0xbd973f6a3f67bf4e,
0xbeac3f783f7bbf35,0x3f7dbf2cbf22be95,0x3f80bf18bf0ebec4,0xbf04bedbbef13f7f,0x3f67bf5cbf550000,0xbf4ebd49bdc93f62,0xbf3ebe16be483f6d,0xbe793f713f75bf46,
0xbf713e793e483f35,0x3e163f3e3f46bf75,0x3d493f4e3f55bf6d,0x3f5cbf67bf623dc9,0x3edb3f043f0ebf80,0x3f18bf80bf7f3ef1,0x3f2cbf7dbf7b3ec4,0xbf783eac3e953f22,
0x3f7ebf39bf22be48,0xbf09bea1bedb3f78,0xbd973f513f62bf6d,0x3f6fbf5fbf4e3d49,0xbf773ecf3e953f0e,0x3e2f3f273f3ebf7d,0x3ee6bf7abf7f3f35,0xbf803f1d3f043eac,
0x3dfb3f313f46bf7b,0x3f58bf73bf673e79,0xbf7f3f133ef13ec4,0x3eb83efc3f18bf80,0x3e89bf6abf753f55,0xbf7c3f423f2c3e16,0x3f65be60bdc9bf35,0x3cc9bf4abf5c3f71,
0xbe48bf0ebf353f80,0xbf553f7b3f6dbec4,0xbf7b3f553f350000,0x3f0e3e483ec4bf6d,0x3e483f0e3f35bf80,0x3f55bf7bbf6d3ec4,0x3f7bbf55bf350000,0xbf0ebe48bec43f6d,
0x3f7bbf55bf358000,0xbf0ebe48bec43f6d,0xbe48bf0ebf353f80,0xbf553f7b3f6dbec4,0xbf7b3f553f358000,0x3f0e3e483ec4bf6d,0x3e483f0e3f35bf80,0x3f55bf7bbf6d3ec4,
0xbf4a3f803f75bf0e,0x3f58bea1bd49bf18,0xbf423e2fbdc93f35,0xbeb83f5f3f78bf67,0x3f77bf6abf463e48,0xbf13bd97beac3f5c,0x3ee63e603ef1bf6d,0x3f31bf7ebf7d3f2c,
0xbf1dbcc9be953f55,0xbf093f733f80bf4e,0x3f27bf7cbf7f3f35,0xbf6f3efc3e793edb,0x3e893ecf3f22bf7b,0x3f51bf7fbf713f04,0xbf653f7a3f62bec4,0x3f39bdfb3e16bf3e,
0x3f2cbe163e48bf35,0x3f04bf67bf7f3f62,0x3f71bf78bf553ec4,0xbf183d49be953f46,0xbf803f4e3f0e0000,0x3e793eac3f22bf75,0xbedb3f5c3f7bbf6d,0x3f7dbf3ebef1bdc9,
0xbf3e3f7d3f7bbf35,0x3f5cbedbbdc9bef1,0x3eac3e793f0ebf6d,0x3f4ebf80bf753f22,0x3d49bf18bf553f80,0xbf783f713f46be95,0xbf673f043e483ec4,0xbe163f2c3f62bf7f,
0x3f6abf7fbf623f0e,0xbf1d3e2fbe793f2c,0x3f58befcbdc9bec4,0x3ea1bf39bf713f7d,0x3cc93ee63f46bf7b,0x3f77bf7abf4e3edb,0xbf513f7e3f75bf35,0x3f42beb83d49bf04,
0x3ecf3d973ef1bf55,0x3f4abf7cbf783f3e,0xbf093f5f3f7fbf6d,0x3f73bf31beacbe16,0xbf803f653f22be48,0x3e893e603f18bf67,0xbf133dfbbe953f35,0xbf273f6f3f80bf5c,
0xbe953f223f6dbf80,0x3f7fbf62bf0e3e48,0x3ef1bdc93ec4bf35,0x3f46bf75bf7b3f55,0x3f75bf46bec40000,0x3dc9bef1bf553f7b,0x3f62bf7fbf6d3f35,0xbf223e95be483f0e,
0xbf753f463ec48000,0xbdc93ef13f55bf7b,0xbf623f7f3f6dbf35,0x3f22be953e48bf0e,0xbe953f223f6dbf80,0x3f7fbf62bf0e3e48,0x3ef1bdc93ec4bf35,0x3f46bf75bf7b3f55,
0x3f51bf1dbdc9be48,0x3ee6bf31bf783f80,0x3eb8bd973ef1bf35,0x3f5fbf7abf713f4e,0x3f58bf77bf753f55,0xbf273ecfbe163edb,0x3f80bf73bf223ec4,0xbdfbbe2fbf2c3f5c,
0xbf133f4a3f7fbf7b,0x3f65bf39be79bd49,0xbf6f3f7f3f62bf35,0x3efcbe603eacbf18,0x3f09be893e95bf0e,0x3f42bf6abf7d3f67,0xbcc93ea13f46bf6d,0x3f7ebf7cbf3e3f04,
0x3f78bf80bf553f35,0xbeac3e16bef13f22,0x3f4ebf67bf7b3f6d,0xbf2c3f04bdc93e95,0x3f5cbf3ebe480000,0x3edbbf18bf753f7f,0x3f7dbf71bf0e3ec4,0x3d49be79bf463f62,
0x3e79bd493f0ebf35,0x3f71bf7dbf623f46,0x3f18bedb3e48bec4,0x3f3ebf5cbf7f3f75,0xbf043f2c3f7bbf80,0x3f67bf4ebe953dc9,0xbe163eac3f55bf6d,0x3f80bf78bf223ef1,
0x3f42bf51bf7f3f7b,0xbf313f1dbd493e16,0x3f5fbf6abf753f6d,0xbf093ee6be793eac,0x3f73bf7abf623f55,0xbeb83e89bedb3f04,0x3f7ebf80bf463f35,0xbe2f3d97bf183f2c,
0x3f27bf133dc9be48,0x3f39bf4abf803f7d,0x3efcbecf3e95bec4,0x3f58bf65bf783f71,0x3ea1be603ef1bf0e,0x3f6fbf77bf673f5c,0x3dfbbcc93f22bf35,0x3f7cbf7fbf4e3f3e,
0xbf353f35bf803f80,0x3f35bf3500000000,0xbf353f35bf803f80,0x3f35bf3500000000,0xbf353f35bf803f80,0x3f35bf3500000000,0xbf353f35bf803f80,0x3f35bf3500000000,
0x3f35bf3580008000,0x3f35bf353f80bf80,0x3f35bf3580008000,0x3f35bf353f80bf80,0x3f35bf3580008000,0x3f35bf353f80bf80,0x3f35bf3580008000,0x3f35bf353f80bf80,
0xbf73bf7a3f753f7b,0xbf6fbf773f713f78,0xbf7ebf803f7f3f80,0xbf7cbf7f3f7d3f80,0xbf42bf513f463f55,0xbf39bf4a3f3e3f4e,0xbf5fbf6a3f623f6d,0xbf58bf653f5c3f67,
0x3ea13e60be95be48,0x3eb83e89beacbe79,0x3dfb3cc9bdc98000,0x3e2f3d97be16bd49,0x3f273f13bf22bf0e,0x3f313f1dbf2cbf18,0x3efc3ecfbef1bec4,0x3f093ee6bf04bedb,
0xbf04bf2c3f0e3f35,0xbedbbf183ef13f22,0xbe16beac3e483ec4,0xbd49be793dc93e95,0xbf78bf803f7b3f80,0xbf71bf7d3f753f7f,0xbf4ebf673f553f6d,0xbf3ebf5c3f463f62,
0x3f5c3f3ebf55bf35,0x3f673f4ebf62bf46,0x3f7d3f71bf7bbf6d,0x3f803f78bf7fbf75,0x3e793d49be488000,0x3eac3e16be95bdc9,0x3f183edbbf0ebec4,0x3f2c3f04bf22bef1,
0x3f093e89bef1be48,0x3f273ecfbf18beac,0xbcc9bea13dc93ec4,0x3dfbbe2fbd493e79,0xbf13bf4a3f223f55,0xbee6bf313f043f3e,0xbf6fbf7f3f753f80,0xbf5fbf7a3f673f7d,
0x3f583f77bf62bf7b,0x3f423f6abf4ebf71,0x3f803f73bf7fbf6d,0x3f7e3f7cbf80bf78,0x3f513f1dbf46bf0e,0x3f653f39bf5cbf2c,0x3eb83d97be958000,0x3efc3e60bedbbe16,
0xbf62bf7f3f6d3f80,0xbf46bf753f553f7b,0xbe95bf223ec43f35,0xbdc9bef13e483f0e,0x3ef13dc9bec40000,0x3f223e95bf0ebe48,0x3f753f46bf6dbf35,0x3f7f3f62bf7bbf55,
0x3ef13dc9bec48000,0x3f223e95bf0ebe48,0x3f753f46bf6dbf35,0x3f7f3f62bf7bbf55,0x3f623f7fbf6dbf80,0x3f463f75bf55bf7b,0x3e953f22bec4bf35,0x3dc93ef1be48bf0e,
0x3cc9bee63dc93f0e,0x3e89be60be163eac,0xbf51bf7e3f623f80,0xbf27bf6f3f3e3f78,0x3f6a3f7fbf75bf7b,0x3f4a3f7cbf5cbf80,0x3f583efcbf46bec4,0x3f733f31bf67bf18,
0x3f803f65bf7fbf55,0x3f773f7abf7dbf71,0x3f133dfbbef18000,0x3f423eb8bf2cbe79,0xbecf3d973e95be48,0xbf1dbe2f3f043d49,0x3f093f5fbf22bf6d,0x3ea13f39bedbbf4e,
0x3f803f4ebf7bbf35,0x3f783f71bf7fbf62,0x3edb3f5cbf0ebf6d,0x3e163f2cbe95bf46,0xbf3ebf7d3f553f80,0xbf04bf673f223f75,0x3eacbe79be483ec4,0x3f183d49bef13dc9,
0x3d493f18be48bf35,0xbe793eac3dc9bef1,0xbf67bf043f553ec4,0xbf7dbf3e3f753f22,0x3f2c3e16bf0e8000,0x3f5c3edbbf46be95,0x3f713f78bf7bbf6d,0x3f4e3f80bf62bf7f,
0xbe893ecf3dc9bf0e,0xbf133d973edbbe79,0x3f653f7abf75bf6d,0x3f313f7ebf4ebf80,0x3f1dbcc9bef13e48,0x3f583ea1bf3ebe16,0xbf27bf7c3f463f80,0xbeb8bf5f3f043f71,
0xbf77bf6a3f7f3f55,0xbf51bf7f3f673f78,0xbee63e603e95bec4,0xbf39bdfb3f18bd49,0x3f4a3f80bf62bf7b,0x3f093f73bf2cbf7d,0x3f423e2fbf228000,0x3f6f3efcbf5cbeac,
0xbf0ebf7b3f353f80,0xbe48bf553ec43f6d,0x3f553e48bf350000,0x3f7b3f0ebf6dbec4,0x3f0e3f7bbf35bf80,0x3e483f55bec4bf6d,0xbf55be483f350000,0xbf7bbf0e3f6d3ec4,
0x3f553e48bf358000,0x3f7b3f0ebf6dbec4,0x3f0e3f7bbf35bf80,0x3e483f55bec4bf6d,0xbf55be483f358000,0xbf7bbf0e3f6d3ec4,0xbf0ebf7b3f353f80,0xbe48bf553ec43f6d,
0x3f773ecfbf62be48,0x3f7c3f42bf80bf18,0xbee6bf7a3f223f80,0xbcc9bf4a3e793f67,0xbf7ebf393f7f3f0e,0xbf58bf733f713f5c,0x3d973f51be95bf6d,0xbeb83efc3e16bf2c,
0x3e893f6abef1bf7b,0xbe2f3f27bd49bf4e,0x3f653e60bf468000,0x3f803f1dbf78bedb,0x3dfbbf313dc93f55,0x3f09bea1beac3f04,0xbf7fbf133f753ec4,0xbf6fbf5f3f7d3f3e,
0xbedb3f043e48bf35,0xbf4e3d493f22be95,0xbf2cbf7d3f553f6d,0xbe79bf713ef13f7f,0xbeacbf783f0e3f80,0x3e16bf3e3dc93f62,0x3f803f18bf7bbec4,0x3f5c3f67bf75bf46,
0xbf67bf5c3f7b3f35,0xbf18bf803f463f75,0x3f3ebe16bf0e3ec4,0x3f783eacbf62bdc9,0x3f713e79bf558000,0x3f7d3f2cbf7fbef1,0xbd493f4ebe48bf6d,0xbf043edb3e95bf22,
0xbcc9bf653e953f7b,0x3efcbf09be793f3e,0xbf513dfb3f22bec4,0xbf7fbecf3f713e16,0x3f6f3f42bf7fbf0e,0x3f1d3f7cbf4ebf67,0xbe60bf773ef13f80,0x3ea1bf31bd493f5c,
0x3f803ee6bf75be48,0x3f5f3f58bf78bf2c,0xbf13bf7e3f463f6d,0xbd97bf6a3eac3f7d,0xbeb83f273dc9bf55,0xbf4a3e2f3f18bedb,0x3f7a3e89bf628000,0x3f733f39bf80bf04,
0xbdc9bf753ec43f80,0x3ef1bf22be483f55,0x3f463f62bf6dbf35,0x3e953f7fbf0ebf7b,0xbf7fbe953f6d0000,0xbf62bf463f7b3f0e,0x3f22bef1bec43f35,0x3f753dc9bf553e48,
0x3f7f3e95bf6d8000,0x3f623f46bf7bbf0e,0xbf223ef13ec4bf35,0xbf75bdc93f55be48,0xbdc9bf753ec43f80,0x3ef1bf22be483f55,0x3f463f62bf6dbf35,0x3e953f7fbf0ebf7b,
0x3f093f77bf46bf55,0xbd973f6fbe79bf80,0x3cc9bf733e953f80,0x3f1dbf13beac3f4e,0x3f7c3dfbbf623e48,0x3f653f31bf7dbedb,0xbf6abf273f7f3ec4,0xbefcbf7a3f3e3f5c,
0xbf583e893f22bf0e,0xbf7fbeb83f783d49,0x3f803ea1bf758000,0x3f4a3f51bf71bf18,0x3e2f3f7ebef1bf7b,0xbee63f393e16bf67,0x3ecfbf42bdc93f6d,0x3f5fbe60bf2c3f04,
0xbf18bf673f553f35,0x3d49bf783e953f7f,0x3f5c3f2cbf7bbec4,0x3eac3f7dbf22bf62,0x3e16bf713e483f80,0x3f3ebf04bef13f46,0x3e793f80bf0ebf6d,0xbedb3f4e3dc9bf75,
0x3f4ebedbbf0e3f35,0x3f803e79bf753dc9,0xbf043f3e3e48bf6d,0xbf713e163f46bef1,0x3f7d3eacbf7b8000,0x3f2c3f5cbf62bf22,0xbf783d493f55bec4,0xbf67bf183f7f3e95,
0x3ea13f7abf22bf55,0xbecf3f5f3d49bf7d,0xbdfbbf803ef13f6d,0x3f13bf42be793f71,0xbd973f7cbe95bf7b,0xbf393f1d3edbbf5c,0x3e89bf6f3dc93f80,0x3f58bee6bf183f3e,
0xbf733e603f46bf0e,0xbf6abefc3f803e16,0x3f7ebcc9bf623ec4,0x3f513f27bf78beac,0xbf7fbe2f3f75be48,0xbf31bf4a3f673f04,0x3f773eb8bf7f8000,0x3f093f65bf4ebf2c,
0x3ec4bf6d00003f80,0x3f6dbec4bf353f35,0xbec43f6d0000bf80,0xbf6d3ec43f35bf35,0x3ec4bf6d00003f80,0x3f6dbec4bf353f35,0xbec43f6d0000bf80,0xbf6d3ec43f35bf35,
0x3f6d3ec4bf808000,0x3ec43f6dbf35bf35,0xbf6dbec43f808000,0xbec4bf6d3f353f35,0x3f6d3ec4bf808000,0x3ec43f6dbf35bf35,0xbf6dbec43f808000,0xbec4bf6d3f353f35,
0xbf273f513e95bf7b,0xbf803dfb3f67bf04,0x3efcbf6abdc93f80,0x3f7abea1bf4e3f2c,0xbf653f093f22bf55,0xbf6fbe893f80be16,0x3f4abf31bef13f6d,0x3f7c3d97bf783eac,
0xbf42bf133f753e48,0xbcc9bf7e3edb3f5c,0x3f5f3ecfbf7f8000,0x3e603f73bf18bf3e,0xbee6bf583f463f0e,0x3eb8bf773d493f7d,0x3f1d3f39bf62bec4,0xbe2f3f7fbe79bf71,
0x3f7dbeacbf553f35,0x3f3e3f04bf75bdc9,0xbf78bd493f7bbec4,0xbedbbf4e3f463ef1,0x3f18bf67be483f80,0x3f80be79bf623f22,0xbf5c3f2c3f0ebf6d,0xbf71be163f7fbe95,
0x3e163f71bf0ebf35,0xbf2c3f5c3e95bf7f,0x3e79bf803e483f6d,0x3f67bf18bf223f62,0x3f4e3edbbf7b8000,0x3d493f78bef1bf46,0xbf04bf3e3f553ec4,0x3eacbf7d3dc93f75,
0xbf13bf1d3f623e48,0x3ea1bf803e163f67,0x3f6f3d97bf7f3ec4,0x3e893f58bf2cbf04,0xbf7a3efc3f46bf55,0xbf42becf3f78bd49,0x3f31bf65be953f80,0x3f7ebe2fbf713f18,
0x3f51bf4abef13f7b,0x3f733cc9bf7d3edb,0xbeb83f7fbdc9bf6d,0xbf773f093f3ebf5c,0xbe60bf5f3f223f0e,0x3f27bf6abe793f80,0x3f393ee6bf758000,0xbdfb3f7cbeacbf4e,
0x3f46bf62bec43f80,0x3f75bdc9bf7b3f0e,0xbf7f3e953f6dbf35,0xbef1bf223f553e48,0x3f223ef1bf6d0000,0xbe953f7fbe48bf55,0x3dc9bf753ec43f35,0x3f62bf46bf0e3f7b,
0x3f223ef1bf6d8000,0xbe953f7fbe48bf55,0x3dc9bf753ec43f35,0x3f62bf46bf0e3f7b,0xbf463f623ec4bf80,0xbf753dc93f7bbf0e,0x3f7fbe95bf6d3f35,0x3ef13f22bf55be48,
0xbf6a3d973f7fbf0e,0xbdfbbf513f183edb,0x3f58bf5fbef13f80,0x3f65bcc9bf803f04,0x3f39bf73be953f7b,0x3f77be60bf783f2c,0x3e2f3f4abf22bec4,0xbf423f6f3eacbf7d,
0x3ecfbf7f3dc93f55,0x3f7ebf13bf4e3f67,0x3f093efcbf628000,0xbee63f80bd49bf5c,0x3f313ea1bf753e48,0xbe893f7abe79bf3e,0xbf7c3f1d3f46bf6d,0xbf27beb83f71be16,
0xbeac3f78be48bf35,0xbf7d3f2c3f46bf75,0x3f80bf18bf553f6d,0x3f043edbbf623dc9,0x3f67bf5cbf0e3f80,0x3f4e3d49bf7f3ef1,0xbf3ebe163f7bbec4,0x3e79bf713e953f22,
0xbf713e793f7bbf35,0xbe16bf3e3f223e95,0x3d493f4ebf0ebec4,0xbf5c3f673ef1bf7f,0x3edb3f04bf558000,0xbf183f803dc9bf62,0x3f2cbf7dbe483f6d,0x3f78beacbf753f46,
0x3f4abcc9bf7f3f0e,0xbe603f65beacbf04,0xbf423f7c3e95bf6d,0xbf6a3e893f7dbf3e,0xbefcbeb83f62be48,0x3f13bf7fbd493f4e,0x3f73bf58bf223f80,0x3f313dfbbf783edb,
0xbf1d3f803dc9bf55,0xbf7a3ee63f71bf5c,0xbf27be2f3f75bec4,0x3ecfbf773e163f2c,0x3f5fbf6fbef13f7b,0x3f51bd97bf803f18,0x3ea13f09bf468000,0xbf393f7e3e79bf67,
0x3f7bbf55bf353f80,0x3f0e3e48bf6d3ec4,0xbe48bf0e3f350000,0x3f55bf7bbec43f6d,0xbf7b3f553f35bf80,0xbf0ebe483f6dbec4,0x3e483f0ebf350000,0xbf553f7b3ec4bf6d,
0x3e483f0ebf358000,0xbf553f7b3ec4bf6d,0x3f7bbf55bf353f80,0x3f0e3e48bf6d3ec4,0xbe48bf0e3f358000,0x3f55bf7bbec43f6d,0xbf7b3f553f35bf80,0xbf0ebe483f6dbec4,
0x3dfbbf393ef13e48,0x3f7abf65bf2c3f7d,0x3f7fbf51bf463f80,0x3ecf3e89bf5c3eac,0xbefc3f6fbdc9bf0e,0xbf7c3f273f67bf78,0xbf733f093f75bf6d,0xbcc9bf1d3f183d49,
0x3f7ebf31bf623f7b,0x3e603ee6bf3e3e16,0x3d973f13bf228000,0xbf6a3f773f04bf71,0xbf5f3eb83f7fbf55,0x3e2fbf423edb3e79,0x3ea1bf583e953ec4,0x3f80bf4abf4e3f80,
0xbf2c3e163f7bbf35,0x3f04bf673dc93ef1,0xbf713f783f0ebf6d,0xbf183d493f75bf22,0x3f80bf4ebf553f80,0x3e793eacbf463e95,0x3edbbf5c3e483ec4,0x3f7dbf3ebf623f7f,
0x3f3ebf7dbe483f35,0x3f5cbedbbf7f3f62,0xbeacbe793f55bec4,0x3f4ebf80be953f46,0xbd493f18bf0e8000,0xbf783f713f22bf75,0x3f67bf04bf7b3f6d,0xbe163f2cbef1bdc9,
0xbf6f3f273f75bf7b,0x3dfbbf133f04bd49,0xbe60be893f46bec4,0x3f65bf80bedb3f4e,0x3f31bf73bdc93f0e,0x3f5fbf09bf7d3f71,0x3f7cbf4abf623f80,0x3d973ecfbf2c3e79,
0x3eb8bf423e953e48,0x3f7ebf51bf5c3f80,0x3f7abf77bf223f6d,0x3ee63cc9bf673f18,0x3f39bea1bf7f3f55,0xbefc3f58be16beac,0xbe2f3f1dbef18000,0xbf7f3f6a3f3ebf78,
0x3f75bf46bf6d3f80,0xbdc93ef1bf0e3e48,0x3f62bf7fbec43f35,0x3f22be95bf7b3f55,0x3e95bf223ec40000,0x3f7fbf62bf553f7b,0xbef13dc93f6dbf35,0x3f46bf75be483f0e,
0xbe953f22bec48000,0xbf7f3f623f55bf7b,0x3ef1bdc9bf6d3f35,0xbf463f753e48bf0e,0x3f75bf46bf6d3f80,0xbdc93ef1bf0e3e48,0x3f62bf7fbec43f35,0x3f22be95bf7b3f55,
0x3f7cbf7ebf223f55,0x3ea1bcc9bf5c3f2c,0x3f6abf42bf753f80,0xbe893f09bedb3e16,0x3e60befc3ef1be48,0x3f7fbf6fbf4e3f71,0x3f39bf65bdc93ec4,0x3f4abf13bf803f78,
0x3e2f3dfbbf463f0e,0xbf733f803f04bf3e,0xbecf3f27be958000,0xbf773f583f67bf7d,0x3f7abf5fbf623f7b,0xbd973eb8bf183eac,0x3f31bee6bf7f3f6d,0xbf1d3f51bd49be79,
0x3f78bf80bf0e3f35,0x3eacbe16bf623f46,0x3f4ebf67be483ec4,0x3f2cbf04bf7f3f75,0x3f5cbf3ebf7b3f80,0xbedb3f18be953dc9,0x3f7dbf71bf553f6d,0xbd493e79bf223ef1,
0x3e79bd49bf553f35,0xbf713f7d3ef1bf22,0x3f18bedbbf7b3f6d,0xbf3e3f5c3dc9be95,0xbf043f2cbe488000,0xbf673f4e3f75bf7f,0xbe163eacbf0e3ec4,0xbf803f783f46bf62,
0x3f7fbf7cbf463f55,0xbcc93dfbbf2c3f18,0x3f77bf6fbf623f6d,0xbe603ea1bf043edb,0x3f65bf58bf753f7b,0xbecf3efcbeac3e79,0x3f4abf39bf7f3f80,0xbf133f27be163d49,
0xbd973e2fbf223f0e,0xbf803f7e3f3ebf4e,0xbe893eb8bef13ec4,0xbf7a3f733f5cbf67,0xbee63f09be953e48,0xbf6a3f5f3f71bf78,0xbf1d3f31bdc98000,0xbf513f423f7dbf80,
0xbf353f35bf803f80,0x3f35bf3500000000,0xbf353f35bf803f80,0x3f35bf3500000000,0xbf353f35bf803f80,0x3f35bf3500000000,0xbf353f35bf803f80,0x3f35bf3500000000,
0x3f35bf3580008000,0x3f35bf353f80bf80,0x3f35bf3580008000,0x3f35bf353f80bf80,0x3f35bf3580008000,0x3f35bf353f80bf80,0x3f35bf3580008000,0x3f35bf353f80bf80,
0xbee6bf093ef13f0e,0xbecfbefc3edb3f04,0xbf1dbf313f223f35,0xbf13bf273f183f2c,0xbd97be2f3dc93e48,0xbcc9bdfb3d493e16,0xbe89beb83e953ec4,0xbe60bea13e793eac,
0x3f653f58bf62bf55,0x3f6a3f5fbf67bf5c,0x3f4a3f39bf46bf35,0x3f513f42bf4ebf3e,0x3f7f3f7cbf7fbf7b,0x3f803f7ebf80bf7d,0x3f773f6fbf75bf6d,0x3f7a3f73bf78bf71,
0x3f5c3f3ebf55bf35,0x3f673f4ebf62bf46,0x3f7d3f71bf7bbf6d,0x3f803f78bf7fbf75,0x3e793d49be480000,0x3eac3e16be95bdc9,0x3f183edbbf0ebec4,0x3f2c3f04bf22bef1,
0x3f043f2cbf0ebf35,0x3edb3f18bef1bf22,0x3e163eacbe48bec4,0x3d493e79bdc9be95,0x3f783f80bf7bbf80,0x3f713f7dbf75bf7f,0x3f4e3f67bf55bf6d,0x3f3e3f5cbf46bf62,
0x3e603efcbe95bf0e,0x3d973eb8be16bedb,0x3f393f65bf46bf6d,0x3f1d3f51bf2cbf5c,0x3f7c3f7ebf7fbf7b,0x3f733f80bf78bf80,0x3f6a3f42bf62bf35,0x3f773f58bf71bf4e,
0xbf7abf5f3f753f55,0xbf7fbf6f3f7d3f67,0xbf31bee63f223ec4,0xbf4abf133f3e3f04,0xbe2f3dfb3dc9be48,0xbea1bcc93e79bd49,0x3ecf3f27bef1bf35,0x3e893f09beacbf18,
0x3f623f7fbf6dbf80,0x3f463f75bf55bf7b,0x3e953f22bec4bf35,0x3dc93ef1be48bf0e,0xbef1bdc93ec40000,0xbf22be953f0e3e48,0xbf75bf463f6d3f35,0xbf7fbf623f7b3f55,
0xbef1bdc93ec48000,0xbf22be953f0e3e48,0xbf75bf463f6d3f35,0xbf7fbf623f7b3f55,0xbf62bf7f3f6d3f80,0xbf46bf753f553f7b,0xbe95bf223ec43f35,0xbdc9bef13e483f0e,
0xbf39bea13f223e48,0xbf5fbf093f4e3edb,0x3e2f3f1dbe95bf35,0xbd973ecfbd49bf04,0xbeb8bf423ef13f55,0xbdfbbf133e793f2c,0xbf7abf773f7f3f6d,0xbf65bf803f713f7d,
0xbf31bf733f463f7b,0xbefcbf583f183f67,0xbf7cbf4a3f753f35,0xbf7fbf6a3f803f5c,0x3f6f3f27bf62bf0e,0x3f7e3f51bf78bf3e,0x3e60be89bdc93ec4,0x3ee6bcc9beac3e16,
0xbd49bf183e483f35,0x3e79beacbdc93ef1,0x3f673f04bf55bec4,0x3f7d3f3ebf75bf22,0xbf2cbe163f0e0000,0xbf5cbedb3f463e95,0xbf71bf783f7b3f6d,0xbf4ebf803f623f7f,
0x3f803f4ebf7bbf35,0x3f783f71bf7fbf62,0x3edb3f5cbf0ebf6d,0x3e163f2cbe95bf46,0xbf3ebf7d3f553f80,0xbf04bf673f223f75,0x3eacbe79be483ec4,0x3f183d49bef13dc9,
0x3efc3f6fbf22bf7b,0x3e2f3f42beacbf5c,0x3f733f09bf62bec4,0x3f803f4abf7dbf2c,0xbdfbbf393e953f55,0x3e60bee6bd493f18,0xbf7fbf513f7f3f35,0xbf6abf773f783f67,
0xbf5fbeb83f463e48,0xbf7cbf273f713f04,0x3ea13f58bef1bf6d,0xbcc93f1dbe16bf3e,0x3f7e3f31bf75bf0e,0x3f7a3f65bf80bf4e,0x3d97bf133dc93f35,0x3ecfbe89be793edb,
0xbf0ebf7b3f353f80,0xbe48bf553ec43f6d,0x3f553e48bf350000,0x3f7b3f0ebf6dbec4,0x3f0e3f7bbf35bf80,0x3e483f55bec4bf6d,0xbf55be483f350000,0xbf7bbf0e3f6d3ec4,
0x3f553e48bf358000,0x3f7b3f0ebf6dbec4,0x3f0e3f7bbf35bf80,0x3e483f55bec4bf6d,0xbf55be483f358000,0xbf7bbf0e3f6d3ec4,0xbf0ebf7b3f353f80,0xbe48bf553ec43f6d,
0x3f5f3f6fbf75bf55,0x3f133f7fbf3ebf7d,0x3ea1bf09bdc93f35,0x3f31bdfbbf043eac,0xbf1dbf803f463f7b,0xbe60bf653edb3f78,0xbf273e2f3ef1bec4,0xbf6abe893f4e3d49,
0xbefc3eb83e95bf0e,0xbf51bd973f2cbe16,0x3f733f58bf7fbf35,0x3f393f7ebf5cbf71,0x3f4a3cc9bf223e48,0x3f7a3ee6bf67be79,0xbf42bf7c3f623f6d,0xbecfbf773f183f80,
0xbf67bf5c3f7b3f35,0xbf18bf803f463f75,0x3f3ebe16bf0e3ec4,0x3f783eacbf62bdc9,0x3f713e79bf550000,0x3f7d3f2cbf7fbef1,0xbd493f4ebe48bf6d,0xbf043edb3e95bf22,
0x3edbbf04be483f35,0x3f4ebd49bf223e95,0x3f2c3f7dbf55bf6d,0x3e793f71bef1bf7f,0x3eac3f78bf0ebf80,0xbe163f3ebdc9bf62,0xbf80bf183f7b3ec4,0xbf5cbf673f753f46,
0x3f393f73bf62bf55,0x3e893f7abf04bf80,0x3e2fbf4a3dc93f6d,0x3f27beb8bedb3f18,0xbf6abd973f46be48,0xbf7ebf133f7d3eac,0x3f583f5fbf75bf35,0x3ee63f80bf2cbf78,
0xbf313ea13ef1bf0e,0xbf77be603f5cbd49,0x3f7c3f1dbf7fbec4,0x3f423f6fbf67bf4e,0xbecfbf7f3f223f7b,0x3dfbbf513e163f71,0xbf093efc3e95bf35,0xbf65bcc93f3ebe79,
0x3dc93f75bec4bf80,0xbef13f223e48bf55,0xbf46bf623f6d3f35,0xbe95bf7f3f0e3f7b,0x3f7f3e95bf6d0000,0x3f623f46bf7bbf0e,0xbf223ef13ec4bf35,0xbf75bdc93f55be48,
0xbf7fbe953f6d8000,0xbf62bf463f7b3f0e,0x3f22bef1bec43f35,0x3f753dc9bf553e48,0x3dc93f75bec4bf80,0xbef13f223e48bf55,0xbf46bf623f6d3f35,0xbe95bf7f3f0e3f7b,
0x3e60bf5f3dc93f7b,0x3f42becfbf043f2c,0xbf393ee63ef1bf35,0xbf7ebe2f3f67be16,0xbf51bf4a3f753f0e,0xbea1bf803f183f71,0x3eb83f7fbf22bf6d,0xbe893f58bd49bf78,
0x3f7a3efcbf7fbe48,0x3f273f6abf5cbf3e,0xbf31bf653f623f35,0xbdfbbf7c3edb3f7d,0x3f13bf1dbe953f55,0x3f73bcc9bf4e3eac,0xbf6f3d973f46bec4,0xbf77bf093f803e79,
0xbf4e3edb3f0ebf35,0xbf80be793f75bdc9,0x3f04bf3ebe483f6d,0x3f71be16bf463ef1,0xbf7dbeac3f7b0000,0xbf2cbf5c3f623f22,0x3f78bd49bf553ec4,0x3f673f18bf7fbe95,
0xbf18bf673f553f35,0x3d49bf783e953f7f,0x3f5c3f2cbf7bbec4,0x3eac3f7dbf22bf62,0x3e16bf713e483f80,0x3f3ebf04bef13f46,0x3e793f80bf0ebf6d,0xbedb3f4e3dc9bf75,
0x3f653f09bf7fbe48,0x3eb83f77bf2cbf4e,0xbf4abf313f753ec4,0xbe2fbf7f3f043f67,0x3f273f51bf62bf0e,0xbcc93f7ebeacbf78,0xbefcbf6a3f463f35,0x3e60bf733e163f80,
0xbee63f583dc9bf7b,0xbf6f3e893f3ebf18,0x3f1dbf39be953f6d,0x3f7cbd97bf5c3edb,0xbf423f133ef1bf55,0xbf80bdfb3f71be79,0x3f5fbecfbf223f35,0x3f7a3ea1bf7d3d49,
0x3ec4bf6d00003f80,0x3f6dbec4bf353f35,0xbec43f6d0000bf80,0xbf6d3ec43f35bf35,0x3ec4bf6d00003f80,0x3f6dbec4bf353f35,0xbec43f6d0000bf80,0xbf6d3ec43f35bf35,
0x3f6d3ec4bf808000,0x3ec43f6dbf35bf35,0xbf6dbec43f808000,0xbec4bf6d3f353f35,0x3f6d3ec4bf808000,0x3ec43f6dbf35bf35,0xbf6dbec43f808000,0xbec4bf6d3f353f35,
0xbf7f3e2f3f62bf0e,0xbf39bf1d3f713e79,0x3f77beb8bf463f35,0x3f583ee6bf7dbd49,0xbf73be603f7fbe48,0xbecfbf5f3f3e3f18,0x3f7e3cc9bf753ec4,0x3f133f42bf5cbedb,
0xbd97bf7c3ef13f55,0x3f31bf4abeac3f78,0x3e893f6fbf22bf35,0xbf093f653e16bf80,0x3ea1bf7a3dc93f7b,0x3f6abefcbf2c3f4e,0xbdfb3f80be95bf6d,0xbf513f273f04bf67,
0x3e163f71bf0ebf35,0xbf2c3f5c3e95bf7f,0x3e79bf803e483f6d,0x3f67bf18bf223f62,0x3f4e3edbbf7b0000,0x3d493f78bef1bf46,0xbf04bf3e3f553ec4,0x3eacbf7d3dc93f75,
0xbf7d3eac3f55bf35,0xbf3ebf043f753dc9,0x3f783d49bf7b3ec4,0x3edb3f4ebf46bef1,0xbf183f673e48bf80,0xbf803e793f62bf22,0x3f5cbf2cbf0e3f6d,0x3f713e16bf7f3e95,
0x3f7cbdfbbf753f0e,0x3ee63f39bf4ebeac,0xbf6a3f273f22bf6d,0xbf5fbe603f80be79,0x3f09bf77bdc93f7b,0x3f7fbeb8bf5c3f3e,0x3cc93f73bef1bf35,0xbf4a3f513edbbf7d,
0xbe2f3f7ebe95bf55,0xbf653f313f18bf71,0xbecfbf423f463ec4,0x3efcbf7abd493f78,0x3f583e89bf7f3e48,0x3d973f6fbf04bf2c,0xbf803ea13f62bf35,0xbf1dbf133f673e16,
0xbf463f623ec4bf80,0xbf753dc93f7bbf0e,0x3f7fbe95bf6d3f35,0x3ef13f22bf55be48,0xbf22bef13f6d0000,0x3e95bf7f3e483f55,0xbdc93f75bec4bf35,0xbf623f463f0ebf7b,
0xbf22bef13f6d8000,0x3e95bf7f3e483f55,0xbdc93f75bec4bf35,0xbf623f463f0ebf7b,0x3f46bf62bec43f80,0x3f75bdc9bf7b3f0e,0xbf7f3e953f6dbf35,0xbef1bf223f553e48,
0x3eb83f27bf46be48,0xbf1d3f7c3e16bf71,0xbf7a3e893f75bf35,0xbea1bf313f3e3e79,0xbf803ee63f62bf55,0xbefcbf093f5c3d49,0x3f13bf7ebdc93f6d,0x3f7fbecfbf673f4e,
0xbf6f3f423f22bf7b,0xbf4abe2f3f7dbeac,0x3e60bf773e953f35,0x3f73bf39bf2c3f78,0x3cc9bf653ef13f0e,0x3f5fbf58bf043f80,0x3f513dfbbf7f3ec4,0xbd973f6abedbbf18,
0x3f71be79bf7b3f35,0x3e163f3ebf22be95,0xbd49bf4e3f0e3ec4,0x3f5cbf67bef13f7f,0xbedbbf043f550000,0x3f18bf80bdc93f62,0xbf2c3f7d3e48bf6d,0xbf783eac3f75bf46,
0xbeac3f78be48bf35,0xbf7d3f2c3f46bf75,0x3f80bf18bf553f6d,0x3f043edbbf623dc9,0x3f67bf5cbf0e3f80,0x3f4e3d49bf7f3ef1,0xbf3ebe163f7bbec4,0x3e79bf713e953f22,
0x3f7ebf39bf463f7b,0x3f093ea1bf673e79,0xbd973f51bef1bec4,0xbf6f3f5f3f18bf80,0xbf773ecf3f75bf55,0xbe2fbf273f2c3e16,0x3ee6bf7a3dc93f35,0x3f80bf1dbf5c3f71,
0x3dfb3f31bf22be48,0xbf583f733edbbf78,0xbf7f3f133f62bf6d,0xbeb8befc3f4ebd49,0x3e89bf6a3e953f0e,0x3f7cbf42bf3e3f7d,0x3f65be60bf7f3f35,0xbcc93f4abf04beac,
0x3f7bbf55bf353f80,0x3f0e3e48bf6d3ec4,0xbe48bf0e3f350000,0x3f55bf7bbec43f6d,0xbf7b3f553f35bf80,0xbf0ebe483f6dbec4,0x3e483f0ebf350000,0xbf553f7b3ec4bf6d,
0x3e483f0ebf358000,0xbf553f7b3ec4bf6d,0x3f7bbf55bf353f80,0x3f0e3e48bf6d3ec4,0xbe48bf0e3f358000,0x3f55bf7bbec43f6d,0xbf7b3f553f35bf80,0xbf0ebe483f6dbec4,
0x3f4abf80be953f55,0x3f58bea1bf803f4e,0x3f42be2fbf7f3f35,0xbeb83f5fbe79bedb,0xbf773f6a3f22bf7b,0xbf13bd973f71bf04,0xbee6be603f62bec4,0x3f31bf7ebe163f3e,
0x3f1d3cc9bf753f0e,0xbf093f73bd49bf18,0xbf273f7c3dc9bf35,0xbf6f3efc3f78bf67,0xbe89becf3f46be48,0x3f51bf7fbeac3f5c,0x3f65bf7abef13f6d,0x3f39bdfbbf7d3f2c,
0x3f3ebf7dbe483f35,0x3f5cbedbbf7f3f62,0xbeacbe793f55bec4,0x3f4ebf80be953f46,0xbd493f18bf0e0000,0xbf783f713f22bf75,0x3f67bf04bf7b3f6d,0xbe163f2cbef1bdc9,
0x3f2cbe16bf7b3f35,0xbf043f67bdc9bef1,0x3f71bf78bf0e3f6d,0x3f18bd49bf753f22,0xbf803f4e3f55bf80,0xbe79beac3f46be95,0xbedb3f5cbe48bec4,0xbf7d3f3e3f62bf7f,
0x3f6abf7fbef13f55,0x3f1dbe2fbf783f3e,0x3f58befcbf7f3f6d,0xbea13f39beacbe16,0x3cc93ee6bf223e48,0xbf773f7a3f18bf67,0xbf513f7e3e95bf35,0xbf423eb83f80bf5c,
0x3ecf3d97bf623f0e,0xbf4a3f7c3e79bf2c,0xbf093f5fbdc9bec4,0xbf733f313f71bf7d,0xbf803f653f46bf7b,0xbe89be603f4ebedb,0xbf133dfb3f75bf35,0x3f27bf6fbd493f04,
0xbf753f463f6dbf80,0x3dc9bef13f0ebe48,0xbf623f7f3ec4bf35,0xbf223e953f7bbf55,0xbe953f22bec40000,0xbf7f3f623f55bf7b,0x3ef1bdc9bf6d3f35,0xbf463f753e48bf0e,
0x3e95bf223ec48000,0x3f7fbf62bf553f7b,0xbef13dc93f6dbf35,0x3f46bf75be483f0e,0xbf753f463f6dbf80,0x3dc9bef13f0ebe48,0xbf623f7f3ec4bf35,0xbf223e953f7bbf55,
0xbf513f1d3f7fbf7b,0x3ee6bf313e793d49,0xbeb83d973f62bf35,0x3f5fbf7abeac3f18,0xbf583f773e95bf0e,0xbf273ecf3f7dbf67,0xbf803f733f46bf6d,0xbdfbbe2f3f3ebf04,
0x3f13bf4a3dc93e48,0x3f65bf39bf783f80,0x3f6fbf7fbef13f35,0x3efcbe60bf713f4e,0xbf093e893f75bf55,0x3f42bf6abe163edb,0x3cc9bea13f22bec4,0x3f7ebf7cbf2c3f5c,
0xbe793d493f55bf35,0x3f71bf7dbef13f22,0xbf183edb3f7bbf6d,0x3f3ebf5cbdc93e95,0x3f04bf2c3e480000,0x3f67bf4ebf753f7f,0x3e16beac3f0ebec4,0x3f80bf78bf463f62,
0x3f78bf80bf0e3f35,0x3eacbe16bf623f46,0x3f4ebf67be483ec4,0x3f2cbf04bf7f3f75,0x3f5cbf3ebf7b3f80,0xbedb3f18be953dc9,0x3f7dbf71bf553f6d,0xbd493e79bf223ef1,
0x3f42bf51bdc93e48,0x3f31bf1dbf803f7d,0x3f5fbf6abe953ec4,0x3f09bee6bf783f71,0x3f73bf7abef13f0e,0x3eb8be89bf673f5c,0x3f7ebf80bf223f35,0x3e2fbd97bf4e3f3e,
0x3f27bf13bf7f3f7b,0xbf393f4a3d49be16,0x3efcbecfbf753f6d,0xbf583f653e79beac,0x3ea1be60bf623f55,0xbf6f3f773edbbf04,0x3dfbbcc9bf463f35,0xbf7c3f7f3f18bf2c,
0xbf353f35bf803f80,0x3f35bf3500000000,0xbf353f35bf803f80,0x3f35bf3500000000,0xbf353f35bf803f80,0x3f35bf3500000000,0xbf353f35bf803f80,0x3f35bf3500000000,
0x3f35bf3580008000,0x3f35bf353f80bf80,0x3f35bf3580008000,0x3f35bf353f80bf80,0x3f35bf3580008000,0x3f35bf353f80bf80,0x3f35bf3580008000,0x3f35bf353f80bf80,
0x3ea13e60be95be48,0x3eb83e89beacbe79,0x3dfb3cc9bdc90000,0x3e2f3d97be16bd49,0x3f273f13bf22bf0e,0x3f313f1dbf2cbf18,0x3efc3ecfbef1bec4,0x3f093ee6bf04bedb,
0x3f733f7abf75bf7b,0x3f6f3f77bf71bf78,0x3f7e3f80bf7fbf80,0x3f7c3f7fbf7dbf80,0x3f423f51bf46bf55,0x3f393f4abf3ebf4e,0x3f5f3f6abf62bf6d,0x3f583f65bf5cbf67,
0x3f043f2cbf0ebf35,0x3edb3f18bef1bf22,0x3e163eacbe48bec4,0x3d493e79bdc9be95,0x3f783f80bf7bbf80,0x3f713f7dbf75bf7f,0x3f4e3f67bf55bf6d,0x3f3e3f5cbf46bf62,
0xbf5cbf3e3f553f35,0xbf67bf4e3f623f46,0xbf7dbf713f7b3f6d,0xbf80bf783f7f3f75,0xbe79bd493e488000,0xbeacbe163e953dc9,0xbf18bedb3f0e3ec4,0xbf2cbf043f223ef1,
0xbf58bf773f623f7b,0xbf42bf6a3f4e3f71,0xbf80bf733f7f3f6d,0xbf7ebf7c3f803f78,0xbf51bf1d3f463f0e,0xbf65bf393f5c3f2c,0xbeb8bd973e950000,0xbefcbe603edb3e16,
0x3f093e89bef1be48,0x3f273ecfbf18beac,0xbcc9bea13dc93ec4,0x3dfbbe2fbd493e79,0xbf13bf4a3f223f55,0xbee6bf313f043f3e,0xbf6fbf7f3f753f80,0xbf5fbf7a3f673f7d,
0xbf62bf7f3f6d3f80,0xbf46bf753f553f7b,0xbe95bf223ec43f35,0xbdc9bef13e483f0e,0x3ef13dc9bec40000,0x3f223e95bf0ebe48,0x3f753f46bf6dbf35,0x3f7f3f62bf7bbf55,
0x3ef13dc9bec48000,0x3f223e95bf0ebe48,0x3f753f46bf6dbf35,0x3f7f3f62bf7bbf55,0x3f623f7fbf6dbf80,0x3f463f75bf55bf7b,0x3e953f22bec4bf35,0x3dc93ef1be48bf0e,
0x3f803f65bf7fbf55,0x3f773f7abf7dbf71,0x3f133dfbbef10000,0x3f423eb8bf2cbe79,0xbecf3d973e95be48,0xbf1dbe2f3f043d49,0x3f093f5fbf22bf6d,0x3ea13f39bedbbf4e,
0xbcc93ee6bdc9bf0e,0xbe893e603e16beac,0x3f513f7ebf62bf80,0x3f273f6fbf3ebf78,0xbf6abf7f3f753f7b,0xbf4abf7c3f5c3f80,0xbf58befc3f463ec4,0xbf73bf313f673f18,
0xbf80bf4e3f7b3f35,0xbf78bf713f7f3f62,0xbedbbf5c3f0e3f6d,0xbe16bf2c3e953f46,0x3f3e3f7dbf55bf80,0x3f043f67bf22bf75,0xbeac3e793e48bec4,0xbf18bd493ef1bdc9,
0xbd49bf183e483f35,0x3e79beacbdc93ef1,0x3f673f04bf55bec4,0x3f7d3f3ebf75bf22,0xbf2cbe163f0e8000,0xbf5cbedb3f463e95,0xbf71bf783f7b3f6d,0xbf4ebf803f623f7f,
0x3f773f6abf7fbf55,0x3f513f7fbf67bf78,0x3ee6be60be953ec4,0x3f393dfbbf183d49,0xbf4abf803f623f7b,0xbf09bf733f2c3f7d,0xbf42be2f3f220000,0xbf6fbefc3f5c3eac,
0xbe893ecf3dc9bf0e,0xbf133d973edbbe79,0x3f653f7abf75bf6d,0x3f313f7ebf4ebf80,0x3f1dbcc9bef13e48,0x3f583ea1bf3ebe16,0xbf27bf7c3f463f80,0xbeb8bf5f3f043f71,
0xbf0ebf7b3f353f80,0xbe48bf553ec43f6d,0x3f553e48bf350000,0x3f7b3f0ebf6dbec4,0x3f0e3f7bbf35bf80,0x3e483f55bec4bf6d,0xbf55be483f350000,0xbf7bbf0e3f6d3ec4,
0x3f553e48bf358000,0x3f7b3f0ebf6dbec4,0x3f0e3f7bbf35bf80,0x3e483f55bec4bf6d,0xbf55be483f358000,0xbf7bbf0e3f6d3ec4,0xbf0ebf7b3f353f80,0xbe48bf553ec43f6d,
0x3e893f6abef1bf7b,0xbe2f3f27bd49bf4e,0x3f653e60bf460000,0x3f803f1dbf78bedb,0x3dfbbf313dc93f55,0x3f09bea1beac3f04,0xbf7fbf133f753ec4,0xbf6fbf5f3f7d3f3e,
0xbf77becf3f623e48,0xbf7cbf423f803f18,0x3ee63f7abf22bf80,0x3cc93f4abe79bf67,0x3f7e3f39bf7fbf0e,0x3f583f73bf71bf5c,0xbd97bf513e953f6d,0x3eb8befcbe163f2c,
0x3edbbf04be483f35,0x3f4ebd49bf223e95,0x3f2c3f7dbf55bf6d,0x3e793f71bef1bf7f,0x3eac3f78bf0ebf80,0xbe163f3ebdc9bf62,0xbf80bf183f7b3ec4,0xbf5cbf673f753f46,
0x3f673f5cbf7bbf35,0x3f183f80bf46bf75,0xbf3e3e163f0ebec4,0xbf78beac3f623dc9,0xbf71be793f558000,0xbf7dbf2c3f7f3ef1,0x3d49bf4e3e483f6d,0x3f04bedbbe953f22,
0xbf80bee63f753e48,0xbf5fbf583f783f2c,0x3f133f7ebf46bf6d,0x3d973f6abeacbf7d,0x3eb8bf27bdc93f55,0x3f4abe2fbf183edb,0xbf7abe893f620000,0xbf73bf393f803f04,
0xbcc9bf653e953f7b,0x3efcbf09be793f3e,0xbf513dfb3f22bec4,0xbf7fbecf3f713e16,0x3f6f3f42bf7fbf0e,0x3f1d3f7cbf4ebf67,0xbe60bf773ef13f80,0x3ea1bf31bd493f5c,
0xbdc9bf753ec43f80,0x3ef1bf22be483f55,0x3f463f62bf6dbf35,0x3e953f7fbf0ebf7b,0xbf7fbe953f6d0000,0xbf62bf463f7b3f0e,0x3f22bef1bec43f35,0x3f753dc9bf553e48,
0x3f7f3e95bf6d8000,0x3f623f46bf7bbf0e,0xbf223ef13ec4bf35,0xbf75bdc93f55be48,0xbdc9bf753ec43f80,0x3ef1bf22be483f55,0x3f463f62bf6dbf35,0x3e953f7fbf0ebf7b,
0xbf583e893f22bf0e,0xbf7fbeb83f783d49,0x3f803ea1bf750000,0x3f4a3f51bf71bf18,0x3e2f3f7ebef1bf7b,0xbee63f393e16bf67,0x3ecfbf42bdc93f6d,0x3f5fbe60bf2c3f04,
0xbf09bf773f463f55,0x3d97bf6f3e793f80,0xbcc93f73be95bf80,0xbf1d3f133eacbf4e,0xbf7cbdfb3f62be48,0xbf65bf313f7d3edb,0x3f6a3f27bf7fbec4,0x3efc3f7abf3ebf5c,
0x3f183f67bf55bf35,0xbd493f78be95bf7f,0xbf5cbf2c3f7b3ec4,0xbeacbf7d3f223f62,0xbe163f71be48bf80,0xbf3e3f043ef1bf46,0xbe79bf803f0e3f6d,0x3edbbf4ebdc93f75,
0xbf4e3edb3f0ebf35,0xbf80be793f75bdc9,0x3f04bf3ebe483f6d,0x3f71be16bf463ef1,0xbf7dbeac3f7b8000,0xbf2cbf5c3f623f22,0x3f78bd49bf553ec4,0x3f673f18bf7fbe95,
0x3f73be60bf463f0e,0x3f6a3efcbf80be16,0xbf7e3cc93f62bec4,0xbf51bf273f783eac,0x3f7f3e2fbf753e48,0x3f313f4abf67bf04,0xbf77beb83f7f0000,0xbf09bf653f4e3f2c,
0x3ea13f7abf22bf55,0xbecf3f5f3d49bf7d,0xbdfbbf803ef13f6d,0x3f13bf42be793f71,0xbd973f7cbe95bf7b,0xbf393f1d3edbbf5c,0x3e89bf6f3dc93f80,0x3f58bee6bf183f3e,
0x3ec4bf6d00003f80,0x3f6dbec4bf353f35,0xbec43f6d0000bf80,0xbf6d3ec43f35bf35,0x3ec4bf6d00003f80,0x3f6dbec4bf353f35,0xbec43f6d0000bf80,0xbf6d3ec43f35bf35,
0x3f6d3ec4bf808000,0x3ec43f6dbf35bf35,0xbf6dbec43f808000,0xbec4bf6d3f353f35,0x3f6d3ec4bf808000,0x3ec43f6dbf35bf35,0xbf6dbec43f808000,0xbec4bf6d3f353f35,
0xbf42bf133f753e48,0xbcc9bf7e3edb3f5c,0x3f5f3ecfbf7f0000,0x3e603f73bf18bf3e,0xbee6bf583f463f0e,0x3eb8bf773d493f7d,0x3f1d3f39bf62bec4,0xbe2f3f7fbe79bf71,
0x3f27bf51be953f7b,0x3f80bdfbbf673f04,0xbefc3f6a3dc9bf80,0xbf7a3ea13f4ebf2c,0x3f65bf09bf223f55,0x3f6f3e89bf803e16,0xbf4a3f313ef1bf6d,0xbf7cbd973f78beac,
0xbf7d3eac3f55bf35,0xbf3ebf043f753dc9,0x3f783d49bf7b3ec4,0x3edb3f4ebf46bef1,0xbf183f673e48bf80,0xbf803e793f62bf22,0x3f5cbf2cbf0e3f6d,0x3f713e16bf7f3e95,
0xbe16bf713f0e3f35,0x3f2cbf5cbe953f7f,0xbe793f80be48bf6d,0xbf673f183f22bf62,0xbf4ebedb3f7b8000,0xbd49bf783ef13f46,0x3f043f3ebf55bec4,0xbeac3f7dbdc9bf75,
0xbf513f4a3ef1bf7b,0xbf73bcc93f7dbedb,0x3eb8bf7f3dc93f6d,0x3f77bf09bf3e3f5c,0x3e603f5fbf22bf0e,0xbf273f6a3e79bf80,0xbf39bee63f750000,0x3dfbbf7c3eac3f4e,
0xbf13bf1d3f623e48,0x3ea1bf803e163f67,0x3f6f3d97bf7f3ec4,0x3e893f58bf2cbf04,0xbf7a3efc3f46bf55,0xbf42becf3f78bd49,0x3f31bf65be953f80,0x3f7ebe2fbf713f18,
0x3f46bf62bec43f80,0x3f75bdc9bf7b3f0e,0xbf7f3e953f6dbf35,0xbef1bf223f553e48,0x3f223ef1bf6d0000,0xbe953f7fbe48bf55,0x3dc9bf753ec43f35,0x3f62bf46bf0e3f7b,
0x3f223ef1bf6d8000,0xbe953f7fbe48bf55,0x3dc9bf753ec43f35,0x3f62bf46bf0e3f7b,0xbf463f623ec4bf80,0xbf753dc93f7bbf0e,0x3f7fbe95bf6d3f35,0x3ef13f22bf55be48,
0x3ecfbf7f3dc93f55,0x3f7ebf13bf4e3f67,0x3f093efcbf620000,0xbee63f80bd49bf5c,0x3f313ea1bf753e48,0xbe893f7abe79bf3e,0xbf7c3f1d3f46bf6d,0xbf27beb83f71be16,
0x3f6abd97bf7f3f0e,0x3dfb3f51bf18bedb,0xbf583f5f3ef1bf80,0xbf653cc93f80bf04,0xbf393f733e95bf7b,0xbf773e603f78bf2c,0xbe2fbf4a3f223ec4,0x3f42bf6fbeac3f7d,
0x3eacbf783e483f35,0x3f7dbf2cbf463f75,0xbf803f183f55bf6d,0xbf04bedb3f62bdc9,0xbf673f5c3f0ebf80,0xbf4ebd493f7fbef1,0x3f3e3e16bf7b3ec4,0xbe793f71be95bf22,
0x3f71be79bf7b3f35,0x3e163f3ebf22be95,0xbd49bf4e3f0e3ec4,0x3f5cbf67bef13f7f,0xbedbbf043f558000,0x3f18bf80bdc93f62,0xbf2c3f7d3e48bf6d,0xbf783eac3f75bf46,
0x3f1dbf80bdc93f55,0x3f7abee6bf713f5c,0x3f273e2fbf753ec4,0xbecf3f77be16bf2c,0xbf5f3f6f3ef1bf7b,0xbf513d973f80bf18,0xbea1bf093f460000,0x3f39bf7ebe793f67,
0x3f4abcc9bf7f3f0e,0xbe603f65beacbf04,0xbf423f7c3e95bf6d,0xbf6a3e893f7dbf3e,0xbefcbeb83f62be48,0x3f13bf7fbd493f4e,0x3f73bf58bf223f80,0x3f313dfbbf783edb,
0x3f7bbf55bf353f80,0x3f0e3e48bf6d3ec4,0xbe48bf0e3f350000,0x3f55bf7bbec43f6d,0xbf7b3f553f35bf80,0xbf0ebe483f6dbec4,0x3e483f0ebf350000,0xbf553f7b3ec4bf6d,
0x3e483f0ebf358000,0xbf553f7b3ec4bf6d,0x3f7bbf55bf353f80,0x3f0e3e48bf6d3ec4,0xbe48bf0e3f358000,0x3f55bf7bbec43f6d,0xbf7b3f553f35bf80,0xbf0ebe483f6dbec4,
0x3f7ebf31bf623f7b,0x3e603ee6bf3e3e16,0x3d973f13bf220000,0xbf6a3f773f04bf71,0xbf5f3eb83f7fbf55,0x3e2fbf423edb3e79,0x3ea1bf583e953ec4,0x3f80bf4abf4e3f80,
0xbdfb3f39bef1be48,0xbf7a3f653f2cbf7d,0xbf7f3f513f46bf80,0xbecfbe893f5cbeac,0x3efcbf6f3dc93f0e,0x3f7cbf27bf673f78,0x3f73bf09bf753f6d,0x3cc93f1dbf18bd49,
0x3f2cbe16bf7b3f35,0xbf043f67bdc9bef1,0x3f71bf78bf0e3f6d,0x3f18bd49bf753f22,0xbf803f4e3f55bf80,0xbe79beac3f46be95,0xbedb3f5cbe48bec4,0xbf7d3f3e3f62bf7f,
0xbf3e3f7d3e48bf35,0xbf5c3edb3f7fbf62,0x3eac3e79bf553ec4,0xbf4e3f803e95bf46,0x3d49bf183f0e8000,0x3f78bf71bf223f75,0xbf673f043f7bbf6d,0x3e16bf2c3ef13dc9,
0xbeb83f42be95be48,0xbf7e3f513f5cbf80,0xbf7a3f773f22bf6d,0xbee6bcc93f67bf18,0xbf393ea13f7fbf55,0x3efcbf583e163eac,0x3e2fbf1d3ef10000,0x3f7fbf6abf3e3f78,
0xbf6f3f273f75bf7b,0x3dfbbf133f04bd49,0xbe60be893f46bec4,0x3f65bf80bedb3f4e,0x3f31bf73bdc93f0e,0x3f5fbf09bf7d3f71,0x3f7cbf4abf623f80,0x3d973ecfbf2c3e79,
0x3f75bf46bf6d3f80,0xbdc93ef1bf0e3e48,0x3f62bf7fbec43f35,0x3f22be95bf7b3f55,0x3e95bf223ec40000,0x3f7fbf62bf553f7b,0xbef13dc93f6dbf35,0x3f46bf75be483f0e,
0xbe953f22bec48000,0xbf7f3f623f55bf7b,0x3ef1bdc9bf6d3f35,0xbf463f753e48bf0e,0x3f75bf46bf6d3f80,0xbdc93ef1bf0e3e48,0x3f62bf7fbec43f35,0x3f22be95bf7b3f55,
0x3e2f3dfbbf463f0e,0xbf733f803f04bf3e,0xbecf3f27be950000,0xbf773f583f67bf7d,0x3f7abf5fbf623f7b,0xbd973eb8bf183eac,0x3f31bee6bf7f3f6d,0xbf1d3f51bd49be79,
0xbf7c3f7e3f22bf55,0xbea13cc93f5cbf2c,0xbf6a3f423f75bf80,0x3e89bf093edbbe16,0xbe603efcbef13e48,0xbf7f3f6f3f4ebf71,0xbf393f653dc9bec4,0xbf4a3f133f80bf78,
0xbf783f803f0ebf35,0xbeac3e163f62bf46,0xbf4e3f673e48bec4,0xbf2c3f043f7fbf75,0xbf5c3f3e3f7bbf80,0x3edbbf183e95bdc9,0xbf7d3f713f55bf6d,0x3d49be793f22bef1,
0xbe793d493f55bf35,0x3f71bf7dbef13f22,0xbf183edb3f7bbf6d,0x3f3ebf5cbdc93e95,0x3f04bf2c3e488000,0x3f67bf4ebf753f7f,0x3e16beac3f0ebec4,0x3f80bf78bf463f62,
0x3d97be2f3f22bf0e,0x3f80bf7ebf3e3f4e,0x3e89beb83ef1bec4,0x3f7abf73bf5c3f67,0x3ee6bf093e95be48,0x3f6abf5fbf713f78,0x3f1dbf313dc90000,0x3f51bf42bf7d3f80,
0x3f7fbf7cbf463f55,0xbcc93dfbbf2c3f18,0x3f77bf6fbf623f6d,0xbe603ea1bf043edb,0x3f65bf58bf753f7b,0xbecf3efcbeac3e79,0x3f4abf39bf7f3f80,0xbf133f27be163d49,
0xbf353f35bf803f80,0x3f35bf3500000000,0xbf353f35bf803f80,0x3f35bf3500000000,0xbf353f35bf803f80,0x3f35bf3500000000,0xbf353f35bf803f80,0x3f35bf3500000000,
0x3f35bf3580008000,0x3f35bf353f80bf80,0x3f35bf3580008000,0x3f35bf353f80bf80,0x3f35bf3580008000,0x3f35bf353f80bf80,0x3f35bf3580008000,0x3f35bf353f80bf80,
0x3f653f58bf62bf55,0x3f6a3f5fbf67bf5c,0x3f4a3f39bf46bf35,0x3f513f42bf4ebf3e,0x3f7f3f7cbf7fbf7b,0x3f803f7ebf80bf7d,0x3f773f6fbf75bf6d,0x3f7a3f73bf78bf71,
0x3ee63f09bef1bf0e,0x3ecf3efcbedbbf04,0x3f1d3f31bf22bf35,0x3f133f27bf18bf2c,0x3d973e2fbdc9be48,0x3cc93dfbbd49be16,0x3e893eb8be95bec4,0x3e603ea1be79beac,
0xbf5cbf3e3f553f35,0xbf67bf4e3f623f46,0xbf7dbf713f7b3f6d,0xbf80bf783f7f3f75,0xbe79bd493e480000,0xbeacbe163e953dc9,0xbf18bedb3f0e3ec4,0xbf2cbf043f223ef1,
0xbf04bf2c3f0e3f35,0xbedbbf183ef13f22,0xbe16beac3e483ec4,0xbd49be793dc93e95,0xbf78bf803f7b3f80,0xbf71bf7d3f753f7f,0xbf4ebf673f553f6d,0xbf3ebf5c3f463f62,
0x3f7a3f5fbf75bf55,0x3f7f3f6fbf7dbf67,0x3f313ee6bf22bec4,0x3f4a3f13bf3ebf04,0x3e2fbdfbbdc93e48,0x3ea13cc9be793d49,0xbecfbf273ef13f35,0xbe89bf093eac3f18,
0x3e603efcbe95bf0e,0x3d973eb8be16bedb,0x3f393f65bf46bf6d,0x3f1d3f51bf2cbf5c,0x3f7c3f7ebf7fbf7b,0x3f733f80bf78bf80,0x3f6a3f42bf62bf35,0x3f773f58bf71bf4e,
0x3f623f7fbf6dbf80,0x3f463f75bf55bf7b,0x3e953f22bec4bf35,0x3dc93ef1be48bf0e,0xbef1bdc93ec40000,0xbf22be953f0e3e48,0xbf75bf463f6d3f35,0xbf7fbf623f7b3f55,
0xbef1bdc93ec48000,0xbf22be953f0e3e48,0xbf75bf463f6d3f35,0xbf7fbf623f7b3f55,0xbf62bf7f3f6d3f80,0xbf46bf753f553f7b,0xbe95bf223ec43f35,0xbdc9bef13e483f0e,
0xbf31bf733f463f7b,0xbefcbf583f183f67,0xbf7cbf4a3f753f35,0xbf7fbf6a3f803f5c,0x3f6f3f27bf62bf0e,0x3f7e3f51bf78bf3e,0x3e60be89bdc93ec4,0x3ee6bcc9beac3e16,
0x3f393ea1bf22be48,0x3f5f3f09bf4ebedb,0xbe2fbf1d3e953f35,0x3d97becf3d493f04,0x3eb83f42bef1bf55,0x3dfb3f13be79bf2c,0x3f7a3f77bf7fbf6d,0x3f653f80bf71bf7d,
0x3d493f18be48bf35,0xbe793eac3dc9bef1,0xbf67bf043f553ec4,0xbf7dbf3e3f753f22,0x3f2c3e16bf0e0000,0x3f5c3edbbf46be95,0x3f713f78bf7bbf6d,0x3f4e3f80bf62bf7f,
0xbf80bf4e3f7b3f35,0xbf78bf713f7f3f62,0xbedbbf5c3f0e3f6d,0xbe16bf2c3e953f46,0x3f3e3f7dbf55bf80,0x3f043f67bf22bf75,0xbeac3e793e48bec4,0xbf18bd493ef1bdc9,
0x3f5f3eb8bf46be48,0x3f7c3f27bf71bf04,0xbea1bf583ef13f6d,0x3cc9bf1d3e163f3e,0xbf7ebf313f753f0e,0xbf7abf653f803f4e,0xbd973f13bdc9bf35,0xbecf3e893e79bedb,
0x3efc3f6fbf22bf7b,0x3e2f3f42beacbf5c,0x3f733f09bf62bec4,0x3f803f4abf7dbf2c,0xbdfbbf393e953f55,0x3e60bee6bd493f18,0xbf7fbf513f7f3f35,0xbf6abf773f783f67,
0xbf0ebf7b3f353f80,0xbe48bf553ec43f6d,0x3f553e48bf350000,0x3f7b3f0ebf6dbec4,0x3f0e3f7bbf35bf80,0x3e483f55bec4bf6d,0xbf55be483f350000,0xbf7bbf0e3f6d3ec4,
0x3f553e48bf358000,0x3f7b3f0ebf6dbec4,0x3f0e3f7bbf35bf80,0x3e483f55bec4bf6d,0xbf55be483f358000,0xbf7bbf0e3f6d3ec4,0xbf0ebf7b3f353f80,0xbe48bf553ec43f6d,
0xbefc3eb83e95bf0e,0xbf51bd973f2cbe16,0x3f733f58bf7fbf35,0x3f393f7ebf5cbf71,0x3f4a3cc9bf223e48,0x3f7a3ee6bf67be79,0xbf42bf7c3f623f6d,0xbecfbf773f183f80,
0xbf5fbf6f3f753f55,0xbf13bf7f3f3e3f7d,0xbea13f093dc9bf35,0xbf313dfb3f04beac,0x3f1d3f80bf46bf7b,0x3e603f65bedbbf78,0x3f27be2fbef13ec4,0x3f6a3e89bf4ebd49,
0x3f673f5cbf7bbf35,0x3f183f80bf46bf75,0xbf3e3e163f0ebec4,0xbf78beac3f623dc9,0xbf71be793f550000,0xbf7dbf2c3f7f3ef1,0x3d49bf4e3e483f6d,0x3f04bedbbe953f22,
0xbedb3f043e48bf35,0xbf4e3d493f22be95,0xbf2cbf7d3f553f6d,0xbe79bf713ef13f7f,0xbeacbf783f0e3f80,0x3e16bf3e3dc93f62,0x3f803f18bf7bbec4,0x3f5c3f67bf75bf46,
0x3f31bea1bef13f0e,0x3f773e60bf5c3d49,0xbf7cbf1d3f7f3ec4,0xbf42bf6f3f673f4e,0x3ecf3f7fbf22bf7b,0xbdfb3f51be16bf71,0x3f09befcbe953f35,0x3f653cc9bf3e3e79,
0x3f393f73bf62bf55,0x3e893f7abf04bf80,0x3e2fbf4a3dc93f6d,0x3f27beb8bedb3f18,0xbf6abd973f46be48,0xbf7ebf133f7d3eac,0x3f583f5fbf75bf35,0x3ee63f80bf2cbf78,
0x3dc93f75bec4bf80,0xbef13f223e48bf55,0xbf46bf623f6d3f35,0xbe95bf7f3f0e3f7b,0x3f7f3e95bf6d0000,0x3f623f46bf7bbf0e,0xbf223ef13ec4bf35,0xbf75bdc93f55be48,
0xbf7fbe953f6d8000,0xbf62bf463f7b3f0e,0x3f22bef1bec43f35,0x3f753dc9bf553e48,0x3dc93f75bec4bf80,0xbef13f223e48bf55,0xbf46bf623f6d3f35,0xbe95bf7f3f0e3f7b,
0x3f7a3efcbf7fbe48,0x3f273f6abf5cbf3e,0xbf31bf653f623f35,0xbdfbbf7c3edb3f7d,0x3f13bf1dbe953f55,0x3f73bcc9bf4e3eac,0xbf6f3d973f46bec4,0xbf77bf093f803e79,
0xbe603f5fbdc9bf7b,0xbf423ecf3f04bf2c,0x3f39bee6bef13f35,0x3f7e3e2fbf673e16,0x3f513f4abf75bf0e,0x3ea13f80bf18bf71,0xbeb8bf7f3f223f6d,0x3e89bf583d493f78,
0x3f4ebedbbf0e3f35,0x3f803e79bf753dc9,0xbf043f3e3e48bf6d,0xbf713e163f46bef1,0x3f7d3eacbf7b0000,0x3f2c3f5cbf62bf22,0xbf783d493f55bec4,0xbf67bf183f7f3e95,
0x3f183f67bf55bf35,0xbd493f78be95bf7f,0xbf5cbf2c3f7b3ec4,0xbeacbf7d3f223f62,0xbe163f71be48bf80,0xbf3e3f043ef1bf46,0xbe79bf803f0e3f6d,0x3edbbf4ebdc93f75,
0x3ee6bf58bdc93f7b,0x3f6fbe89bf3e3f18,0xbf1d3f393e95bf6d,0xbf7c3d973f5cbedb,0x3f42bf13bef13f55,0x3f803dfbbf713e79,0xbf5f3ecf3f22bf35,0xbf7abea13f7dbd49,
0x3f653f09bf7fbe48,0x3eb83f77bf2cbf4e,0xbf4abf313f753ec4,0xbe2fbf7f3f043f67,0x3f273f51bf62bf0e,0xbcc93f7ebeacbf78,0xbefcbf6a3f463f35,0x3e60bf733e163f80,
0x3ec4bf6d00003f80,0x3f6dbec4bf353f35,0xbec43f6d0000bf80,0xbf6d3ec43f35bf35,0x3ec4bf6d00003f80,0x3f6dbec4bf353f35,0xbec43f6d0000bf80,0xbf6d3ec43f35bf35,
0x3f6d3ec4bf808000,0x3ec43f6dbf35bf35,0xbf6dbec43f808000,0xbec4bf6d3f353f35,0x3f6d3ec4bf808000,0x3ec43f6dbf35bf35,0xbf6dbec43f808000,0xbec4bf6d3f353f35,
0xbd97bf7c3ef13f55,0x3f31bf4abeac3f78,0x3e893f6fbf22bf35,0xbf093f653e16bf80,0x3ea1bf7a3dc93f7b,0x3f6abefcbf2c3f4e,0xbdfb3f80be95bf6d,0xbf513f273f04bf67,
0x3f7fbe2fbf623f0e,0x3f393f1dbf71be79,0xbf773eb83f46bf35,0xbf58bee63f7d3d49,0x3f733e60bf7f3e48,0x3ecf3f5fbf3ebf18,0xbf7ebcc93f75bec4,0xbf13bf423f5c3edb,
0xbe16bf713f0e3f35,0x3f2cbf5cbe953f7f,0xbe793f80be48bf6d,0xbf673f183f22bf62,0xbf4ebedb3f7b0000,0xbd49bf783ef13f46,0x3f043f3ebf55bec4,0xbeac3f7dbdc9bf75,
0x3f7dbeacbf553f35,0x3f3e3f04bf75bdc9,0xbf78bd493f7bbec4,0xbedbbf4e3f463ef1,0x3f18bf67be483f80,0x3f80be79bf623f22,0xbf5c3f2c3f0ebf6d,0xbf71be163f7fbe95,
0x3e2fbf7e3e953f55,0x3f65bf31bf183f71,0x3ecf3f42bf46bec4,0xbefc3f7a3d49bf78,0xbf58be893f7fbe48,0xbd97bf6f3f043f2c,0x3f80bea1bf623f35,0x3f1d3f13bf67be16,
0x3f7cbdfbbf753f0e,0x3ee63f39bf4ebeac,0xbf6a3f273f22bf6d,0xbf5fbe603f80be79,0x3f09bf77bdc93f7b,0x3f7fbeb8bf5c3f3e,0x3cc93f73bef1bf35,0xbf4a3f513edbbf7d,
0xbf463f623ec4bf80,0xbf753dc93f7bbf0e,0x3f7fbe95bf6d3f35,0x3ef13f22bf55be48,0xbf22bef13f6d0000,0x3e95bf7f3e483f55,0xbdc93f75bec4bf35,0xbf623f463f0ebf7b,
0xbf22bef13f6d8000,0x3e95bf7f3e483f55,0xbdc93f75bec4bf35,0xbf623f463f0ebf7b,0x3f46bf62bec43f80,0x3f75bdc9bf7b3f0e,0xbf7f3e953f6dbf35,0xbef1bf223f553e48,
0xbf6f3f423f22bf7b,0xbf4abe2f3f7dbeac,0x3e60bf773e953f35,0x3f73bf39bf2c3f78,0x3cc9bf653ef13f0e,0x3f5fbf58bf043f80,0x3f513dfbbf7f3ec4,0xbd973f6abedbbf18,
0xbeb8bf273f463e48,0x3f1dbf7cbe163f71,0x3f7abe89bf753f35,0x3ea13f31bf3ebe79,0x3f80bee6bf623f55,0x3efc3f09bf5cbd49,0xbf133f7e3dc9bf6d,0xbf7f3ecf3f67bf4e,
0xbf713e793f7bbf35,0xbe16bf3e3f223e95,0x3d493f4ebf0ebec4,0xbf5c3f673ef1bf7f,0x3edb3f04bf550000,0xbf183f803dc9bf62,0x3f2cbf7dbe483f6d,0x3f78beacbf753f46,
0x3eacbf783e483f35,0x3f7dbf2cbf463f75,0xbf803f183f55bf6d,0xbf04bedb3f62bdc9,0xbf673f5c3f0ebf80,0xbf4ebd493f7fbef1,0x3f3e3e16bf7b3ec4,0xbe793f71be95bf22,
0xbdfbbf313f223e48,0x3f58bf73bedb3f78,0x3f7fbf13bf623f6d,0x3eb83efcbf4e3d49,0xbe893f6abe95bf0e,0xbf7c3f423f3ebf7d,0xbf653e603f7fbf35,0x3cc9bf4a3f043eac,
0x3f7ebf39bf463f7b,0x3f093ea1bf673e79,0xbd973f51bef1bec4,0xbf6f3f5f3f18bf80,0xbf773ecf3f75bf55,0xbe2fbf273f2c3e16,0x3ee6bf7a3dc93f35,0x3f80bf1dbf5c3f71,
0x3f7bbf55bf353f80,0x3f0e3e48bf6d3ec4,0xbe48bf0e3f350000,0x3f55bf7bbec43f6d,0xbf7b3f553f35bf80,0xbf0ebe483f6dbec4,0x3e483f0ebf350000,0xbf553f7b3ec4bf6d,
0x3e483f0ebf358000,0xbf553f7b3ec4bf6d,0x3f7bbf55bf353f80,0x3f0e3e48bf6d3ec4,0xbe48bf0e3f358000,0x3f55bf7bbec43f6d,0xbf7b3f553f35bf80,0xbf0ebe483f6dbec4,
0x3f1d3cc9bf753f0e,0xbf093f73bd49bf18,0xbf273f7c3dc9bf35,0xbf6f3efc3f78bf67,0xbe89becf3f46be48,0x3f51bf7fbeac3f5c,0x3f65bf7abef13f6d,0x3f39bdfbbf7d3f2c,
0xbf4a3f803e95bf55,0xbf583ea13f80bf4e,0xbf423e2f3f7fbf35,0x3eb8bf5f3e793edb,0x3f77bf6abf223f7b,0x3f133d97bf713f04,0x3ee63e60bf623ec4,0xbf313f7e3e16bf3e,
0xbf3e3f7d3e48bf35,0xbf5c3edb3f7fbf62,0x3eac3e79bf553ec4,0xbf4e3f803e95bf46,0x3d49bf183f0e0000,0x3f78bf71bf223f75,0xbf673f043f7bbf6d,0x3e16bf2c3ef13dc9,
0xbf2c3e163f7bbf35,0x3f04bf673dc93ef1,0xbf713f783f0ebf6d,0xbf183d493f75bf22,0x3f80bf4ebf553f80,0x3e793eacbf463e95,0x3edbbf5c3e483ec4,0x3f7dbf3ebf623f7f,
0xbecfbd973f62bf0e,0x3f4abf7cbe793f2c,0x3f09bf5f3dc93ec4,0x3f73bf31bf713f7d,0x3f80bf65bf463f7b,0x3e893e60bf4e3edb,0x3f13bdfbbf753f35,0xbf273f6f3d49bf04,
0x3f6abf7fbef13f55,0x3f1dbe2fbf783f3e,0x3f58befcbf7f3f6d,0xbea13f39beacbe16,0x3cc93ee6bf223e48,0xbf773f7a3f18bf67,0xbf513f7e3e95bf35,0xbf423eb83f80bf5c,
0xbf753f463f6dbf80,0x3dc9bef13f0ebe48,0xbf623f7f3ec4bf35,0xbf223e953f7bbf55,0xbe953f22bec40000,0xbf7f3f623f55bf7b,0x3ef1bdc9bf6d3f35,0xbf463f753e48bf0e,
0x3e95bf223ec48000,0x3f7fbf62bf553f7b,0xbef13dc93f6dbf35,0x3f46bf75be483f0e,0xbf753f463f6dbf80,0x3dc9bef13f0ebe48,0xbf623f7f3ec4bf35,0xbf223e953f7bbf55,
0x3f13bf4a3dc93e48,0x3f65bf39bf783f80,0x3f6fbf7fbef13f35,0x3efcbe60bf713f4e,0xbf093e893f75bf55,0x3f42bf6abe163edb,0x3cc9bea13f22bec4,0x3f7ebf7cbf2c3f5c,
0x3f51bf1dbf7f3f7b,0xbee63f31be79bd49,0x3eb8bd97bf623f35,0xbf5f3f7a3eacbf18,0x3f58bf77be953f0e,0x3f27becfbf7d3f67,0x3f80bf73bf463f6d,0x3dfb3e2fbf3e3f04,
0x3e79bd49bf553f35,0xbf713f7d3ef1bf22,0x3f18bedbbf7b3f6d,0xbf3e3f5c3dc9be95,0xbf043f2cbe480000,0xbf673f4e3f75bf7f,0xbe163eacbf0e3ec4,0xbf803f783f46bf62,
0xbf783f803f0ebf35,0xbeac3e163f62bf46,0xbf4e3f673e48bec4,0xbf2c3f043f7fbf75,0xbf5c3f3e3f7bbf80,0x3edbbf183e95bdc9,0xbf7d3f713f55bf6d,0x3d49be793f22bef1,
0xbf273f133f7fbf7b,0x3f39bf4abd493e16,0xbefc3ecf3f75bf6d,0x3f58bf65be793eac,0xbea13e603f62bf55,0x3f6fbf77bedb3f04,0xbdfb3cc93f46bf35,0x3f7cbf7fbf183f2c,
0x3f42bf51bdc93e48,0x3f31bf1dbf803f7d,0x3f5fbf6abe953ec4,0x3f09bee6bf783f71,0x3f73bf7abef13f0e,0x3eb8be89bf673f5c,0x3f7ebf80bf223f35,0x3e2fbd97bf4e3f3e,
0xbf353f35bf803f80,0x3f35bf3500000000,0xbf353f35bf803f80,0x3f35bf3500000000,0xbf353f35bf803f80,0x3f35bf3500000000,0xbf353f35bf803f80,0x3f35bf3500000000,
0x3f35bf3580008000,0x3f35bf353f80bf80,0x3f35bf3580008000,0x3f35bf353f80bf80,0x3f35bf3580008000,0x3f35bf353f80bf80,0x3f35bf3580008000,0x3f35bf353f80bf80,
0x3f733f7abf75bf7b,0x3f6f3f77bf71bf78,0x3f7e3f80bf7fbf80,0x3f7c3f7fbf7dbf80,0x3f423f51bf46bf55,0x3f393f4abf3ebf4e,0x3f5f3f6abf62bf6d,0x3f583f65bf5cbf67,
0xbea1be603e953e48,0xbeb8be893eac3e79,0xbdfbbcc93dc98000,0xbe2fbd973e163d49,0xbf27bf133f223f0e,0xbf31bf1d3f2c3f18,0xbefcbecf3ef13ec4,0xbf09bee63f043edb,
0xbf04bf2c3f0e3f35,0xbedbbf183ef13f22,0xbe16beac3e483ec4,0xbd49be793dc93e95,0xbf78bf803f7b3f80,0xbf71bf7d3f753f7f,0xbf4ebf673f553f6d,0xbf3ebf5c3f463f62,
0x3f5c3f3ebf55bf35,0x3f673f4ebf62bf46,0x3f7d3f71bf7bbf6d,0x3f803f78bf7fbf75,0x3e793d49be488000,0x3eac3e16be95bdc9,0x3f183edbbf0ebec4,0x3f2c3f04bf22bef1,
0xbf09be893ef13e48,0xbf27becf3f183eac,0x3cc93ea1bdc9bec4,0xbdfb3e2f3d49be79,0x3f133f4abf22bf55,0x3ee63f31bf04bf3e,0x3f6f3f7fbf75bf80,0x3f5f3f7abf67bf7d,
0xbf58bf773f623f7b,0xbf42bf6a3f4e3f71,0xbf80bf733f7f3f6d,0xbf7ebf7c3f803f78,0xbf51bf1d3f463f0e,0xbf65bf393f5c3f2c,0xbeb8bd973e958000,0xbefcbe603edb3e16,
0xbf62bf7f3f6d3f80,0xbf46bf753f553f7b,0xbe95bf223ec43f35,0xbdc9bef13e483f0e,0x3ef13dc9bec40000,0x3f223e95bf0ebe48,0x3f753f46bf6dbf35,0x3f7f3f62bf7bbf55,
0x3ef13dc9bec48000,0x3f223e95bf0ebe48,0x3f753f46bf6dbf35,0x3f7f3f62bf7bbf55,0x3f623f7fbf6dbf80,0x3f463f75bf55bf7b,0x3e953f22bec4bf35,0x3dc93ef1be48bf0e,
0xbcc93ee6bdc9bf0e,0xbe893e603e16beac,0x3f513f7ebf62bf80,0x3f273f6fbf3ebf78,0xbf6abf7f3f753f7b,0xbf4abf7c3f5c3f80,0xbf58befc3f463ec4,0xbf73bf313f673f18,
0xbf80bf653f7f3f55,0xbf77bf7a3f7d3f71,0xbf13bdfb3ef18000,0xbf42beb83f2c3e79,0x3ecfbd97be953e48,0x3f1d3e2fbf04bd49,0xbf09bf5f3f223f6d,0xbea1bf393edb3f4e,
0x3f803f4ebf7bbf35,0x3f783f71bf7fbf62,0x3edb3f5cbf0ebf6d,0x3e163f2cbe95bf46,0xbf3ebf7d3f553f80,0xbf04bf673f223f75,0x3eacbe79be483ec4,0x3f183d49bef13dc9,
0x3d493f18be48bf35,0xbe793eac3dc9bef1,0xbf67bf043f553ec4,0xbf7dbf3e3f753f22,0x3f2c3e16bf0e8000,0x3f5c3edbbf46be95,0x3f713f78bf7bbf6d,0x3f4e3f80bf62bf7f,
0x3e89becfbdc93f0e,0x3f13bd97bedb3e79,0xbf65bf7a3f753f6d,0xbf31bf7e3f4e3f80,0xbf1d3cc93ef1be48,0xbf58bea13f3e3e16,0x3f273f7cbf46bf80,0x3eb83f5fbf04bf71,
0x3f773f6abf7fbf55,0x3f513f7fbf67bf78,0x3ee6be60be953ec4,0x3f393dfbbf183d49,0xbf4abf803f623f7b,0xbf09bf733f2c3f7d,0xbf42be2f3f228000,0xbf6fbefc3f5c3eac,
0xbf0ebf7b3f353f80,0xbe48bf553ec43f6d,0x3f553e48bf350000,0x3f7b3f0ebf6dbec4,0x3f0e3f7bbf35bf80,0x3e483f55bec4bf6d,0xbf55be483f350000,0xbf7bbf0e3f6d3ec4,
0x3f553e48bf358000,0x3f7b3f0ebf6dbec4,0x3f0e3f7bbf35bf80,0x3e483f55bec4bf6d,0xbf55be483f358000,0xbf7bbf0e3f6d3ec4,0xbf0ebf7b3f353f80,0xbe48bf553ec43f6d,
0xbf77becf3f623e48,0xbf7cbf423f803f18,0x3ee63f7abf22bf80,0x3cc93f4abe79bf67,0x3f7e3f39bf7fbf0e,0x3f583f73bf71bf5c,0xbd97bf513e953f6d,0x3eb8befcbe163f2c,
0xbe89bf6a3ef13f7b,0x3e2fbf273d493f4e,0xbf65be603f468000,0xbf80bf1d3f783edb,0xbdfb3f31bdc9bf55,0xbf093ea13eacbf04,0x3f7f3f13bf75bec4,0x3f6f3f5fbf7dbf3e,
0xbedb3f043e48bf35,0xbf4e3d493f22be95,0xbf2cbf7d3f553f6d,0xbe79bf713ef13f7f,0xbeacbf783f0e3f80,0x3e16bf3e3dc93f62,0x3f803f18bf7bbec4,0x3f5c3f67bf75bf46,
0xbf67bf5c3f7b3f35,0xbf18bf803f463f75,0x3f3ebe16bf0e3ec4,0x3f783eacbf62bdc9,0x3f713e79bf558000,0x3f7d3f2cbf7fbef1,0xbd493f4ebe48bf6d,0xbf043edb3e95bf22,
0x3cc93f65be95bf7b,0xbefc3f093e79bf3e,0x3f51bdfbbf223ec4,0x3f7f3ecfbf71be16,0xbf6fbf423f7f3f0e,0xbf1dbf7c3f4e3f67,0x3e603f77bef1bf80,0xbea13f313d49bf5c,
0xbf80bee63f753e48,0xbf5fbf583f783f2c,0x3f133f7ebf46bf6d,0x3d973f6abeacbf7d,0x3eb8bf27bdc93f55,0x3f4abe2fbf183edb,0xbf7abe893f628000,0xbf73bf393f803f04,
0xbdc9bf753ec43f80,0x3ef1bf22be483f55,0x3f463f62bf6dbf35,0x3e953f7fbf0ebf7b,0xbf7fbe953f6d0000,0xbf62bf463f7b3f0e,0x3f22bef1bec43f35,0x3f753dc9bf553e48,
0x3f7f3e95bf6d8000,0x3f623f46bf7bbf0e,0xbf223ef13ec4bf35,0xbf75bdc93f55be48,0xbdc9bf753ec43f80,0x3ef1bf22be483f55,0x3f463f62bf6dbf35,0x3e953f7fbf0ebf7b,
0xbf09bf773f463f55,0x3d97bf6f3e793f80,0xbcc93f73be95bf80,0xbf1d3f133eacbf4e,0xbf7cbdfb3f62be48,0xbf65bf313f7d3edb,0x3f6a3f27bf7fbec4,0x3efc3f7abf3ebf5c,
0x3f58be89bf223f0e,0x3f7f3eb8bf78bd49,0xbf80bea13f758000,0xbf4abf513f713f18,0xbe2fbf7e3ef13f7b,0x3ee6bf39be163f67,0xbecf3f423dc9bf6d,0xbf5f3e603f2cbf04,
0xbf18bf673f553f35,0x3d49bf783e953f7f,0x3f5c3f2cbf7bbec4,0x3eac3f7dbf22bf62,0x3e16bf713e483f80,0x3f3ebf04bef13f46,0x3e793f80bf0ebf6d,0xbedb3f4e3dc9bf75,
0x3f4ebedbbf0e3f35,0x3f803e79bf753dc9,0xbf043f3e3e48bf6d,0xbf713e163f46bef1,0x3f7d3eacbf7b8000,0x3f2c3f5cbf62bf22,0xbf783d493f55bec4,0xbf67bf183f7f3e95,
0xbea1bf7a3f223f55,0x3ecfbf5fbd493f7d,0x3dfb3f80bef1bf6d,0xbf133f423e79bf71,0x3d97bf7c3e953f7b,0x3f39bf1dbedb3f5c,0xbe893f6fbdc9bf80,0xbf583ee63f18bf3e,
0x3f73be60bf463f0e,0x3f6a3efcbf80be16,0xbf7e3cc93f62bec4,0xbf51bf273f783eac,0x3f7f3e2fbf753e48,0x3f313f4abf67bf04,0xbf77beb83f7f8000,0xbf09bf653f4e3f2c,
0x3ec4bf6d00003f80,0x3f6dbec4bf353f35,0xbec43f6d0000bf80,0xbf6d3ec43f35bf35,0x3ec4bf6d00003f80,0x3f6dbec4bf353f35,0xbec43f6d0000bf80,0xbf6d3ec43f35bf35,
0x3f6d3ec4bf808000,0x3ec43f6dbf35bf35,0xbf6dbec43f808000,0xbec4bf6d3f353f35,0x3f6d3ec4bf808000,0x3ec43f6dbf35bf35,0xbf6dbec43f808000,0xbec4bf6d3f353f35,
0x3f27bf51be953f7b,0x3f80bdfbbf673f04,0xbefc3f6a3dc9bf80,0xbf7a3ea13f4ebf2c,0x3f65bf09bf223f55,0x3f6f3e89bf803e16,0xbf4a3f313ef1bf6d,0xbf7cbd973f78beac,
0x3f423f13bf75be48,0x3cc93f7ebedbbf5c,0xbf5fbecf3f7f8000,0xbe60bf733f183f3e,0x3ee63f58bf46bf0e,0xbeb83f77bd49bf7d,0xbf1dbf393f623ec4,0x3e2fbf7f3e793f71,
0x3f7dbeacbf553f35,0x3f3e3f04bf75bdc9,0xbf78bd493f7bbec4,0xbedbbf4e3f463ef1,0x3f18bf67be483f80,0x3f80be79bf623f22,0xbf5c3f2c3f0ebf6d,0xbf71be163f7fbe95,
0x3e163f71bf0ebf35,0xbf2c3f5c3e95bf7f,0x3e79bf803e483f6d,0x3f67bf18bf223f62,0x3f4e3edbbf7b8000,0x3d493f78bef1bf46,0xbf04bf3e3f553ec4,0x3eacbf7d3dc93f75,
0x3f133f1dbf62be48,0xbea13f80be16bf67,0xbf6fbd973f7fbec4,0xbe89bf583f2c3f04,0x3f7abefcbf463f55,0x3f423ecfbf783d49,0xbf313f653e95bf80,0xbf7e3e2f3f71bf18,
0xbf513f4a3ef1bf7b,0xbf73bcc93f7dbedb,0x3eb8bf7f3dc93f6d,0x3f77bf09bf3e3f5c,0x3e603f5fbf22bf0e,0xbf273f6a3e79bf80,0xbf39bee63f758000,0x3dfbbf7c3eac3f4e,
0x3f46bf62bec43f80,0x3f75bdc9bf7b3f0e,0xbf7f3e953f6dbf35,0xbef1bf223f553e48,0x3f223ef1bf6d0000,0xbe953f7fbe48bf55,0x3dc9bf753ec43f35,0x3f62bf46bf0e3f7b,
0x3f223ef1bf6d8000,0xbe953f7fbe48bf55,0x3dc9bf753ec43f35,0x3f62bf46bf0e3f7b,0xbf463f623ec4bf80,0xbf753dc93f7bbf0e,0x3f7fbe95bf6d3f35,0x3ef13f22bf55be48,
0x3f6abd97bf7f3f0e,0x3dfb3f51bf18bedb,0xbf583f5f3ef1bf80,0xbf653cc93f80bf04,0xbf393f733e95bf7b,0xbf773e603f78bf2c,0xbe2fbf4a3f223ec4,0x3f42bf6fbeac3f7d,
0xbecf3f7fbdc9bf55,0xbf7e3f133f4ebf67,0xbf09befc3f628000,0x3ee6bf803d493f5c,0xbf31bea13f75be48,0x3e89bf7a3e793f3e,0x3f7cbf1dbf463f6d,0x3f273eb8bf713e16,
0xbeac3f78be48bf35,0xbf7d3f2c3f46bf75,0x3f80bf18bf553f6d,0x3f043edbbf623dc9,0x3f67bf5cbf0e3f80,0x3f4e3d49bf7f3ef1,0xbf3ebe163f7bbec4,0x3e79bf713e953f22,
0xbf713e793f7bbf35,0xbe16bf3e3f223e95,0x3d493f4ebf0ebec4,0xbf5c3f673ef1bf7f,0x3edb3f04bf558000,0xbf183f803dc9bf62,0x3f2cbf7dbe483f6d,0x3f78beacbf753f46,
0xbf4a3cc93f7fbf0e,0x3e60bf653eac3f04,0x3f42bf7cbe953f6d,0x3f6abe89bf7d3f3e,0x3efc3eb8bf623e48,0xbf133f7f3d49bf4e,0xbf733f583f22bf80,0xbf31bdfb3f78bedb,
0x3f1dbf80bdc93f55,0x3f7abee6bf713f5c,0x3f273e2fbf753ec4,0xbecf3f77be16bf2c,0xbf5f3f6f3ef1bf7b,0xbf513d973f80bf18,0xbea1bf093f468000,0x3f39bf7ebe793f67,
0x3f7bbf55bf353f80,0x3f0e3e48bf6d3ec4,0xbe48bf0e3f350000,0x3f55bf7bbec43f6d,0xbf7b3f553f35bf80,0xbf0ebe483f6dbec4,0x3e483f0ebf350000,0xbf553f7b3ec4bf6d,
0x3e483f0ebf358000,0xbf553f7b3ec4bf6d,0x3f7bbf55bf353f80,0x3f0e3e48bf6d3ec4,0xbe48bf0e3f358000,0x3f55bf7bbec43f6d,0xbf7b3f553f35bf80,0xbf0ebe483f6dbec4,
0xbdfb3f39bef1be48,0xbf7a3f653f2cbf7d,0xbf7f3f513f46bf80,0xbecfbe893f5cbeac,0x3efcbf6f3dc93f0e,0x3f7cbf27bf673f78,0x3f73bf09bf753f6d,0x3cc93f1dbf18bd49,
0xbf7e3f313f62bf7b,0xbe60bee63f3ebe16,0xbd97bf133f228000,0x3f6abf77bf043f71,0x3f5fbeb8bf7f3f55,0xbe2f3f42bedbbe79,0xbea13f58be95bec4,0xbf803f4a3f4ebf80,
0xbf2c3e163f7bbf35,0x3f04bf673dc93ef1,0xbf713f783f0ebf6d,0xbf183d493f75bf22,0x3f80bf4ebf553f80,0x3e793eacbf463e95,0x3edbbf5c3e483ec4,0x3f7dbf3ebf623f7f,
0x3f3ebf7dbe483f35,0x3f5cbedbbf7f3f62,0xbeacbe793f55bec4,0x3f4ebf80be953f46,0xbd493f18bf0e8000,0xbf783f713f22bf75,0x3f67bf04bf7b3f6d,0xbe163f2cbef1bdc9,
0x3f6fbf27bf753f7b,0xbdfb3f13bf043d49,0x3e603e89bf463ec4,0xbf653f803edbbf4e,0xbf313f733dc9bf0e,0xbf5f3f093f7dbf71,0xbf7c3f4a3f62bf80,0xbd97becf3f2cbe79,
0xbeb83f42be95be48,0xbf7e3f513f5cbf80,0xbf7a3f773f22bf6d,0xbee6bcc93f67bf18,0xbf393ea13f7fbf55,0x3efcbf583e163eac,0x3e2fbf1d3ef18000,0x3f7fbf6abf3e3f78,
0x3f75bf46bf6d3f80,0xbdc93ef1bf0e3e48,0x3f62bf7fbec43f35,0x3f22be95bf7b3f55,0x3e95bf223ec40000,0x3f7fbf62bf553f7b,0xbef13dc93f6dbf35,0x3f46bf75be483f0e,
0xbe953f22bec48000,0xbf7f3f623f55bf7b,0x3ef1bdc9bf6d3f35,0xbf463f753e48bf0e,0x3f75bf46bf6d3f80,0xbdc93ef1bf0e3e48,0x3f62bf7fbec43f35,0x3f22be95bf7b3f55,
0xbf7c3f7e3f22bf55,0xbea13cc93f5cbf2c,0xbf6a3f423f75bf80,0x3e89bf093edbbe16,0xbe603efcbef13e48,0xbf7f3f6f3f4ebf71,0xbf393f653dc9bec4,0xbf4a3f133f80bf78,
0xbe2fbdfb3f46bf0e,0x3f73bf80bf043f3e,0x3ecfbf273e958000,0x3f77bf58bf673f7d,0xbf7a3f5f3f62bf7b,0x3d97beb83f18beac,0xbf313ee63f7fbf6d,0x3f1dbf513d493e79,
0x3f78bf80bf0e3f35,0x3eacbe16bf623f46,0x3f4ebf67be483ec4,0x3f2cbf04bf7f3f75,0x3f5cbf3ebf7b3f80,0xbedb3f18be953dc9,0x3f7dbf71bf553f6d,0xbd493e79bf223ef1,
0x3e79bd49bf553f35,0xbf713f7d3ef1bf22,0x3f18bedbbf7b3f6d,0xbf3e3f5c3dc9be95,0xbf043f2cbe488000,0xbf673f4e3f75bf7f,0xbe163eacbf0e3ec4,0xbf803f783f46bf62,
0xbf7f3f7c3f46bf55,0x3cc9bdfb3f2cbf18,0xbf773f6f3f62bf6d,0x3e60bea13f04bedb,0xbf653f583f75bf7b,0x3ecfbefc3eacbe79,0xbf4a3f393f7fbf80,0x3f13bf273e16bd49,
0x3d97be2f3f22bf0e,0x3f80bf7ebf3e3f4e,0x3e89beb83ef1bec4,0x3f7abf73bf5c3f67,0x3ee6bf093e95be48,0x3f6abf5fbf713f78,0x3f1dbf313dc98000,0x3f51bf42bf7d3f80,
0xbf353f35bf803f80,0x3f35bf3500000000,0xbf353f35bf803f80,0x3f35bf3500000000,0xbf353f35bf803f80,0x3f35bf3500000000,0xbf353f35bf803f80,0x3f35bf3500000000,
0x3f35bf3580008000,0x3f35bf353f80bf80,0x3f35bf3580008000,0x3f35bf353f80bf80,0x3f35bf3580008000,0x3f35bf353f80bf80,0x3f35bf3580008000,0x3f35bf353f80bf80,
0x3ee63f09bef1bf0e,0x3ecf3efcbedbbf04,0x3f1d3f31bf22bf35,0x3f133f27bf18bf2c,0x3d973e2fbdc9be48,0x3cc93dfbbd49be16,0x3e893eb8be95bec4,0x3e603ea1be79beac,
0xbf65bf583f623f55,0xbf6abf5f3f673f5c,0xbf4abf393f463f35,0xbf51bf423f4e3f3e,0xbf7fbf7c3f7f3f7b,0xbf80bf7e3f803f7d,0xbf77bf6f3f753f6d,0xbf7abf733f783f71,
0x3f5c3f3ebf55bf35,0x3f673f4ebf62bf46,0x3f7d3f71bf7bbf6d,0x3f803f78bf7fbf75,0x3e793d49be480000,0x3eac3e16be95bdc9,0x3f183edbbf0ebec4,0x3f2c3f04bf22bef1,
0x3f043f2cbf0ebf35,0x3edb3f18bef1bf22,0x3e163eacbe48bec4,0x3d493e79bdc9be95,0x3f783f80bf7bbf80,0x3f713f7dbf75bf7f,0x3f4e3f67bf55bf6d,0x3f3e3f5cbf46bf62,
0xbe60befc3e953f0e,0xbd97beb83e163edb,0xbf39bf653f463f6d,0xbf1dbf513f2c3f5c,0xbf7cbf7e3f7f3f7b,0xbf73bf803f783f80,0xbf6abf423f623f35,0xbf77bf583f713f4e,
0x3f7a3f5fbf75bf55,0x3f7f3f6fbf7dbf67,0x3f313ee6bf22bec4,0x3f4a3f13bf3ebf04,0x3e2fbdfbbdc93e48,0x3ea13cc9be793d49,0xbecfbf273ef13f35,0xbe89bf093eac3f18,
0x3f623f7fbf6dbf80,0x3f463f75bf55bf7b,0x3e953f22bec4bf35,0x3dc93ef1be48bf0e,0xbef1bdc93ec40000,0xbf22be953f0e3e48,0xbf75bf463f6d3f35,0xbf7fbf623f7b3f55,
0xbef1bdc93ec48000,0xbf22be953f0e3e48,0xbf75bf463f6d3f35,0xbf7fbf623f7b3f55,0xbf62bf7f3f6d3f80,0xbf46bf753f553f7b,0xbe95bf223ec43f35,0xbdc9bef13e483f0e,
0x3f393ea1bf22be48,0x3f5f3f09bf4ebedb,0xbe2fbf1d3e953f35,0x3d97becf3d493f04,0x3eb83f42bef1bf55,0x3dfb3f13be79bf2c,0x3f7a3f77bf7fbf6d,0x3f653f80bf71bf7d,
0x3f313f73bf46bf7b,0x3efc3f58bf18bf67,0x3f7c3f4abf75bf35,0x3f7f3f6abf80bf5c,0xbf6fbf273f623f0e,0xbf7ebf513f783f3e,0xbe603e893dc9bec4,0xbee63cc93eacbe16,
0xbd49bf183e483f35,0x3e79beacbdc93ef1,0x3f673f04bf55bec4,0x3f7d3f3ebf75bf22,0xbf2cbe163f0e0000,0xbf5cbedb3f463e95,0xbf71bf783f7b3f6d,0xbf4ebf803f623f7f,
0x3f803f4ebf7bbf35,0x3f783f71bf7fbf62,0x3edb3f5cbf0ebf6d,0x3e163f2cbe95bf46,0xbf3ebf7d3f553f80,0xbf04bf673f223f75,0x3eacbe79be483ec4,0x3f183d49bef13dc9,
0xbefcbf6f3f223f7b,0xbe2fbf423eac3f5c,0xbf73bf093f623ec4,0xbf80bf4a3f7d3f2c,0x3dfb3f39be95bf55,0xbe603ee63d49bf18,0x3f7f3f51bf7fbf35,0x3f6a3f77bf78bf67,
0x3f5f3eb8bf46be48,0x3f7c3f27bf71bf04,0xbea1bf583ef13f6d,0x3cc9bf1d3e163f3e,0xbf7ebf313f753f0e,0xbf7abf653f803f4e,0xbd973f13bdc9bf35,0xbecf3e893e79bedb,
0xbf0ebf7b3f353f80,0xbe48bf553ec43f6d,0x3f553e48bf350000,0x3f7b3f0ebf6dbec4,0x3f0e3f7bbf35bf80,0x3e483f55bec4bf6d,0xbf55be483f350000,0xbf7bbf0e3f6d3ec4,
0x3f553e48bf358000,0x3f7b3f0ebf6dbec4,0x3f0e3f7bbf35bf80,0x3e483f55bec4bf6d,0xbf55be483f358000,0xbf7bbf0e3f6d3ec4,0xbf0ebf7b3f353f80,0xbe48bf553ec43f6d,
0xbf5fbf6f3f753f55,0xbf13bf7f3f3e3f7d,0xbea13f093dc9bf35,0xbf313dfb3f04beac,0x3f1d3f80bf46bf7b,0x3e603f65bedbbf78,0x3f27be2fbef13ec4,0x3f6a3e89bf4ebd49,
0x3efcbeb8be953f0e,0x3f513d97bf2c3e16,0xbf73bf583f7f3f35,0xbf39bf7e3f5c3f71,0xbf4abcc93f22be48,0xbf7abee63f673e79,0x3f423f7cbf62bf6d,0x3ecf3f77bf18bf80,
0xbf67bf5c3f7b3f35,0xbf18bf803f463f75,0x3f3ebe16bf0e3ec4,0x3f783eacbf62bdc9,0x3f713e79bf550000,0x3f7d3f2cbf7fbef1,0xbd493f4ebe48bf6d,0xbf043edb3e95bf22,
0x3edbbf04be483f35,0x3f4ebd49bf223e95,0x3f2c3f7dbf55bf6d,0x3e793f71bef1bf7f,0x3eac3f78bf0ebf80,0xbe163f3ebdc9bf62,0xbf80bf183f7b3ec4,0xbf5cbf673f753f46,
0xbf39bf733f623f55,0xbe89bf7a3f043f80,0xbe2f3f4abdc9bf6d,0xbf273eb83edbbf18,0x3f6a3d97bf463e48,0x3f7e3f13bf7dbeac,0xbf58bf5f3f753f35,0xbee6bf803f2c3f78,
0x3f31bea1bef13f0e,0x3f773e60bf5c3d49,0xbf7cbf1d3f7f3ec4,0xbf42bf6f3f673f4e,0x3ecf3f7fbf22bf7b,0xbdfb3f51be16bf71,0x3f09befcbe953f35,0x3f653cc9bf3e3e79,
0x3dc93f75bec4bf80,0xbef13f223e48bf55,0xbf46bf623f6d3f35,0xbe95bf7f3f0e3f7b,0x3f7f3e95bf6d0000,0x3f623f46bf7bbf0e,0xbf223ef13ec4bf35,0xbf75bdc93f55be48,
0xbf7fbe953f6d8000,0xbf62bf463f7b3f0e,0x3f22bef1bec43f35,0x3f753dc9bf553e48,0x3dc93f75bec4bf80,0xbef13f223e48bf55,0xbf46bf623f6d3f35,0xbe95bf7f3f0e3f7b,
0xbe603f5fbdc9bf7b,0xbf423ecf3f04bf2c,0x3f39bee6bef13f35,0x3f7e3e2fbf673e16,0x3f513f4abf75bf0e,0x3ea13f80bf18bf71,0xbeb8bf7f3f223f6d,0x3e89bf583d493f78,
0xbf7abefc3f7f3e48,0xbf27bf6a3f5c3f3e,0x3f313f65bf62bf35,0x3dfb3f7cbedbbf7d,0xbf133f1d3e95bf55,0xbf733cc93f4ebeac,0x3f6fbd97bf463ec4,0x3f773f09bf80be79,
0xbf4e3edb3f0ebf35,0xbf80be793f75bdc9,0x3f04bf3ebe483f6d,0x3f71be16bf463ef1,0xbf7dbeac3f7b0000,0xbf2cbf5c3f623f22,0x3f78bd49bf553ec4,0x3f673f18bf7fbe95,
0xbf18bf673f553f35,0x3d49bf783e953f7f,0x3f5c3f2cbf7bbec4,0x3eac3f7dbf22bf62,0x3e16bf713e483f80,0x3f3ebf04bef13f46,0x3e793f80bf0ebf6d,0xbedb3f4e3dc9bf75,
0xbf65bf093f7f3e48,0xbeb8bf773f2c3f4e,0x3f4a3f31bf75bec4,0x3e2f3f7fbf04bf67,0xbf27bf513f623f0e,0x3cc9bf7e3eac3f78,0x3efc3f6abf46bf35,0xbe603f73be16bf80,
0x3ee6bf58bdc93f7b,0x3f6fbe89bf3e3f18,0xbf1d3f393e95bf6d,0xbf7c3d973f5cbedb,0x3f42bf13bef13f55,0x3f803dfbbf713e79,0xbf5f3ecf3f22bf35,0xbf7abea13f7dbd49,
0x3ec4bf6d00003f80,0x3f6dbec4bf353f35,0xbec43f6d0000bf80,0xbf6d3ec43f35bf35,0x3ec4bf6d00003f80,0x3f6dbec4bf353f35,0xbec43f6d0000bf80,0xbf6d3ec43f35bf35,
0x3f6d3ec4bf808000,0x3ec43f6dbf35bf35,0xbf6dbec43f808000,0xbec4bf6d3f353f35,0x3f6d3ec4bf808000,0x3ec43f6dbf35bf35,0xbf6dbec43f808000,0xbec4bf6d3f353f35,
0x3f7fbe2fbf623f0e,0x3f393f1dbf71be79,0xbf773eb83f46bf35,0xbf58bee63f7d3d49,0x3f733e60bf7f3e48,0x3ecf3f5fbf3ebf18,0xbf7ebcc93f75bec4,0xbf13bf423f5c3edb,
0x3d973f7cbef1bf55,0xbf313f4a3eacbf78,0xbe89bf6f3f223f35,0x3f09bf65be163f80,0xbea13f7abdc9bf7b,0xbf6a3efc3f2cbf4e,0x3dfbbf803e953f6d,0x3f51bf27bf043f67,
0x3e163f71bf0ebf35,0xbf2c3f5c3e95bf7f,0x3e79bf803e483f6d,0x3f67bf18bf223f62,0x3f4e3edbbf7b0000,0x3d493f78bef1bf46,0xbf04bf3e3f553ec4,0x3eacbf7d3dc93f75,
0xbf7d3eac3f55bf35,0xbf3ebf043f753dc9,0x3f783d49bf7b3ec4,0x3edb3f4ebf46bef1,0xbf183f673e48bf80,0xbf803e793f62bf22,0x3f5cbf2cbf0e3f6d,0x3f713e16bf7f3e95,
0xbf7c3dfb3f75bf0e,0xbee6bf393f4e3eac,0x3f6abf27bf223f6d,0x3f5f3e60bf803e79,0xbf093f773dc9bf7b,0xbf7f3eb83f5cbf3e,0xbcc9bf733ef13f35,0x3f4abf51bedb3f7d,
0x3e2fbf7e3e953f55,0x3f65bf31bf183f71,0x3ecf3f42bf46bec4,0xbefc3f7a3d49bf78,0xbf58be893f7fbe48,0xbd97bf6f3f043f2c,0x3f80bea1bf623f35,0x3f1d3f13bf67be16,
0xbf463f623ec4bf80,0xbf753dc93f7bbf0e,0x3f7fbe95bf6d3f35,0x3ef13f22bf55be48,0xbf22bef13f6d0000,0x3e95bf7f3e483f55,0xbdc93f75bec4bf35,0xbf623f463f0ebf7b,
0xbf22bef13f6d8000,0x3e95bf7f3e483f55,0xbdc93f75bec4bf35,0xbf623f463f0ebf7b,0x3f46bf62bec43f80,0x3f75bdc9bf7b3f0e,0xbf7f3e953f6dbf35,0xbef1bf223f553e48,
0xbeb8bf273f463e48,0x3f1dbf7cbe163f71,0x3f7abe89bf753f35,0x3ea13f31bf3ebe79,0x3f80bee6bf623f55,0x3efc3f09bf5cbd49,0xbf133f7e3dc9bf6d,0xbf7f3ecf3f67bf4e,
0x3f6fbf42bf223f7b,0x3f4a3e2fbf7d3eac,0xbe603f77be95bf35,0xbf733f393f2cbf78,0xbcc93f65bef1bf0e,0xbf5f3f583f04bf80,0xbf51bdfb3f7fbec4,0x3d97bf6a3edb3f18,
0x3f71be79bf7b3f35,0x3e163f3ebf22be95,0xbd49bf4e3f0e3ec4,0x3f5cbf67bef13f7f,0xbedbbf043f550000,0x3f18bf80bdc93f62,0xbf2c3f7d3e48bf6d,0xbf783eac3f75bf46,
0xbeac3f78be48bf35,0xbf7d3f2c3f46bf75,0x3f80bf18bf553f6d,0x3f043edbbf623dc9,0x3f67bf5cbf0e3f80,0x3f4e3d49bf7f3ef1,0xbf3ebe163f7bbec4,0x3e79bf713e953f22,
0xbf7e3f393f46bf7b,0xbf09bea13f67be79,0x3d97bf513ef13ec4,0x3f6fbf5fbf183f80,0x3f77becfbf753f55,0x3e2f3f27bf2cbe16,0xbee63f7abdc9bf35,0xbf803f1d3f5cbf71,
0xbdfbbf313f223e48,0x3f58bf73bedb3f78,0x3f7fbf13bf623f6d,0x3eb83efcbf4e3d49,0xbe893f6abe95bf0e,0xbf7c3f423f3ebf7d,0xbf653e603f7fbf35,0x3cc9bf4a3f043eac,
0x3f7bbf55bf353f80,0x3f0e3e48bf6d3ec4,0xbe48bf0e3f350000,0x3f55bf7bbec43f6d,0xbf7b3f553f35bf80,0xbf0ebe483f6dbec4,0x3e483f0ebf350000,0xbf553f7b3ec4bf6d,
0x3e483f0ebf358000,0xbf553f7b3ec4bf6d,0x3f7bbf55bf353f80,0x3f0e3e48bf6d3ec4,0xbe48bf0e3f358000,0x3f55bf7bbec43f6d,0xbf7b3f553f35bf80,0xbf0ebe483f6dbec4,
0xbf4a3f803e95bf55,0xbf583ea13f80bf4e,0xbf423e2f3f7fbf35,0x3eb8bf5f3e793edb,0x3f77bf6abf223f7b,0x3f133d97bf713f04,0x3ee63e60bf623ec4,0xbf313f7e3e16bf3e,
0xbf1dbcc93f75bf0e,0x3f09bf733d493f18,0x3f27bf7cbdc93f35,0x3f6fbefcbf783f67,0x3e893ecfbf463e48,0xbf513f7f3eacbf5c,0xbf653f7a3ef1bf6d,0xbf393dfb3f7dbf2c,
0x3f3ebf7dbe483f35,0x3f5cbedbbf7f3f62,0xbeacbe793f55bec4,0x3f4ebf80be953f46,0xbd493f18bf0e0000,0xbf783f713f22bf75,0x3f67bf04bf7b3f6d,0xbe163f2cbef1bdc9,
0x3f2cbe16bf7b3f35,0xbf043f67bdc9bef1,0x3f71bf78bf0e3f6d,0x3f18bd49bf753f22,0xbf803f4e3f55bf80,0xbe79beac3f46be95,0xbedb3f5cbe48bec4,0xbf7d3f3e3f62bf7f,
0xbf6a3f7f3ef1bf55,0xbf1d3e2f3f78bf3e,0xbf583efc3f7fbf6d,0x3ea1bf393eac3e16,0xbcc9bee63f22be48,0x3f77bf7abf183f67,0x3f51bf7ebe953f35,0x3f42beb8bf803f5c,
0xbecfbd973f62bf0e,0x3f4abf7cbe793f2c,0x3f09bf5f3dc93ec4,0x3f73bf31bf713f7d,0x3f80bf65bf463f7b,0x3e893e60bf4e3edb,0x3f13bdfbbf753f35,0xbf273f6f3d49bf04,
0xbf753f463f6dbf80,0x3dc9bef13f0ebe48,0xbf623f7f3ec4bf35,0xbf223e953f7bbf55,0xbe953f22bec40000,0xbf7f3f623f55bf7b,0x3ef1bdc9bf6d3f35,0xbf463f753e48bf0e,
0x3e95bf223ec48000,0x3f7fbf62bf553f7b,0xbef13dc93f6dbf35,0x3f46bf75be483f0e,0xbf753f463f6dbf80,0x3dc9bef13f0ebe48,0xbf623f7f3ec4bf35,0xbf223e953f7bbf55,
0x3f51bf1dbf7f3f7b,0xbee63f31be79bd49,0x3eb8bd97bf623f35,0xbf5f3f7a3eacbf18,0x3f58bf77be953f0e,0x3f27becfbf7d3f67,0x3f80bf73bf463f6d,0x3dfb3e2fbf3e3f04,
0xbf133f4abdc9be48,0xbf653f393f78bf80,0xbf6f3f7f3ef1bf35,0xbefc3e603f71bf4e,0x3f09be89bf753f55,0xbf423f6a3e16bedb,0xbcc93ea1bf223ec4,0xbf7e3f7c3f2cbf5c,
0xbe793d493f55bf35,0x3f71bf7dbef13f22,0xbf183edb3f7bbf6d,0x3f3ebf5cbdc93e95,0x3f04bf2c3e480000,0x3f67bf4ebf753f7f,0x3e16beac3f0ebec4,0x3f80bf78bf463f62,
0x3f78bf80bf0e3f35,0x3eacbe16bf623f46,0x3f4ebf67be483ec4,0x3f2cbf04bf7f3f75,0x3f5cbf3ebf7b3f80,0xbedb3f18be953dc9,0x3f7dbf71bf553f6d,0xbd493e79bf223ef1,
0xbf423f513dc9be48,0xbf313f1d3f80bf7d,0xbf5f3f6a3e95bec4,0xbf093ee63f78bf71,0xbf733f7a3ef1bf0e,0xbeb83e893f67bf5c,0xbf7e3f803f22bf35,0xbe2f3d973f4ebf3e,
0xbf273f133f7fbf7b,0x3f39bf4abd493e16,0xbefc3ecf3f75bf6d,0x3f58bf65be793eac,0xbea13e603f62bf55,0x3f6fbf77bedb3f04,0xbdfb3cc93f46bf35,0x3f7cbf7fbf183f2c,
0xbf353f35bf803f80,0x3f35bf3500000000,0xbf353f35bf803f80,0x3f35bf3500000000,0xbf353f35bf803f80,0x3f35bf3500000000,0xbf353f35bf803f80,0x3f35bf3500000000,
0x3f35bf3580008000,0x3f35bf353f80bf80,0x3f35bf3580008000,0x3f35bf353f80bf80,0x3f35bf3580008000,0x3f35bf353f80bf80,0x3f35bf3580008000,0x3f35bf353f80bf80,
0xbea1be603e953e48,0xbeb8be893eac3e79,0xbdfbbcc93dc90000,0xbe2fbd973e163d49,0xbf27bf133f223f0e,0xbf31bf1d3f2c3f18,0xbefcbecf3ef13ec4,0xbf09bee63f043edb,
0xbf73bf7a3f753f7b,0xbf6fbf773f713f78,0xbf7ebf803f7f3f80,0xbf7cbf7f3f7d3f80,0xbf42bf513f463f55,0xbf39bf4a3f3e3f4e,0xbf5fbf6a3f623f6d,0xbf58bf653f5c3f67,
0x3f043f2cbf0ebf35,0x3edb3f18bef1bf22,0x3e163eacbe48bec4,0x3d493e79bdc9be95,0x3f783f80bf7bbf80,0x3f713f7dbf75bf7f,0x3f4e3f67bf55bf6d,0x3f3e3f5cbf46bf62,
0xbf5cbf3e3f553f35,0xbf67bf4e3f623f46,0xbf7dbf713f7b3f6d,0xbf80bf783f7f3f75,0xbe79bd493e488000,0xbeacbe163e953dc9,0xbf18bedb3f0e3ec4,0xbf2cbf043f223ef1,
0x3f583f77bf62bf7b,0x3f423f6abf4ebf71,0x3f803f73bf7fbf6d,0x3f7e3f7cbf80bf78,0x3f513f1dbf46bf0e,0x3f653f39bf5cbf2c,0x3eb83d97be950000,0x3efc3e60bedbbe16,
0xbf09be893ef13e48,0xbf27becf3f183eac,0x3cc93ea1bdc9bec4,0xbdfb3e2f3d49be79,0x3f133f4abf22bf55,0x3ee63f31bf04bf3e,0x3f6f3f7fbf75bf80,0x3f5f3f7abf67bf7d,
0xbf62bf7f3f6d3f80,0xbf46bf753f553f7b,0xbe95bf223ec43f35,0xbdc9bef13e483f0e,0x3ef13dc9bec40000,0x3f223e95bf0ebe48,0x3f753f46bf6dbf35,0x3f7f3f62bf7bbf55,
0x3ef13dc9bec48000,0x3f223e95bf0ebe48,0x3f753f46bf6dbf35,0x3f7f3f62bf7bbf55,0x3f623f7fbf6dbf80,0x3f463f75bf55bf7b,0x3e953f22bec4bf35,0x3dc93ef1be48bf0e,
0xbf80bf653f7f3f55,0xbf77bf7a3f7d3f71,0xbf13bdfb3ef10000,0xbf42beb83f2c3e79,0x3ecfbd97be953e48,0x3f1d3e2fbf04bd49,0xbf09bf5f3f223f6d,0xbea1bf393edb3f4e,
0x3cc9bee63dc93f0e,0x3e89be60be163eac,0xbf51bf7e3f623f80,0xbf27bf6f3f3e3f78,0x3f6a3f7fbf75bf7b,0x3f4a3f7cbf5cbf80,0x3f583efcbf46bec4,0x3f733f31bf67bf18,
0xbf80bf4e3f7b3f35,0xbf78bf713f7f3f62,0xbedbbf5c3f0e3f6d,0xbe16bf2c3e953f46,0x3f3e3f7dbf55bf80,0x3f043f67bf22bf75,0xbeac3e793e48bec4,0xbf18bd493ef1bdc9,
0xbd49bf183e483f35,0x3e79beacbdc93ef1,0x3f673f04bf55bec4,0x3f7d3f3ebf75bf22,0xbf2cbe163f0e8000,0xbf5cbedb3f463e95,0xbf71bf783f7b3f6d,0xbf4ebf803f623f7f,
0xbf77bf6a3f7f3f55,0xbf51bf7f3f673f78,0xbee63e603e95bec4,0xbf39bdfb3f18bd49,0x3f4a3f80bf62bf7b,0x3f093f73bf2cbf7d,0x3f423e2fbf220000,0x3f6f3efcbf5cbeac,
0x3e89becfbdc93f0e,0x3f13bd97bedb3e79,0xbf65bf7a3f753f6d,0xbf31bf7e3f4e3f80,0xbf1d3cc93ef1be48,0xbf58bea13f3e3e16,0x3f273f7cbf46bf80,0x3eb83f5fbf04bf71,
0xbf0ebf7b3f353f80,0xbe48bf553ec43f6d,0x3f553e48bf350000,0x3f7b3f0ebf6dbec4,0x3f0e3f7bbf35bf80,0x3e483f55bec4bf6d,0xbf55be483f350000,0xbf7bbf0e3f6d3ec4,
0x3f553e48bf358000,0x3f7b3f0ebf6dbec4,0x3f0e3f7bbf35bf80,0x3e483f55bec4bf6d,0xbf55be483f358000,0xbf7bbf0e3f6d3ec4,0xbf0ebf7b3f353f80,0xbe48bf553ec43f6d,
0xbe89bf6a3ef13f7b,0x3e2fbf273d493f4e,0xbf65be603f460000,0xbf80bf1d3f783edb,0xbdfb3f31bdc9bf55,0xbf093ea13eacbf04,0x3f7f3f13bf75bec4,0x3f6f3f5fbf7dbf3e,
0x3f773ecfbf62be48,0x3f7c3f42bf80bf18,0xbee6bf7a3f223f80,0xbcc9bf4a3e793f67,0xbf7ebf393f7f3f0e,0xbf58bf733f713f5c,0x3d973f51be95bf6d,0xbeb83efc3e16bf2c,
0x3edbbf04be483f35,0x3f4ebd49bf223e95,0x3f2c3f7dbf55bf6d,0x3e793f71bef1bf7f,0x3eac3f78bf0ebf80,0xbe163f3ebdc9bf62,0xbf80bf183f7b3ec4,0xbf5cbf673f753f46,
0x3f673f5cbf7bbf35,0x3f183f80bf46bf75,0xbf3e3e163f0ebec4,0xbf78beac3f623dc9,0xbf71be793f558000,0xbf7dbf2c3f7f3ef1,0x3d49bf4e3e483f6d,0x3f04bedbbe953f22,
0x3f803ee6bf75be48,0x3f5f3f58bf78bf2c,0xbf13bf7e3f463f6d,0xbd97bf6a3eac3f7d,0xbeb83f273dc9bf55,0xbf4a3e2f3f18bedb,0x3f7a3e89bf620000,0x3f733f39bf80bf04,
0x3cc93f65be95bf7b,0xbefc3f093e79bf3e,0x3f51bdfbbf223ec4,0x3f7f3ecfbf71be16,0xbf6fbf423f7f3f0e,0xbf1dbf7c3f4e3f67,0x3e603f77bef1bf80,0xbea13f313d49bf5c,
0xbdc9bf753ec43f80,0x3ef1bf22be483f55,0x3f463f62bf6dbf35,0x3e953f7fbf0ebf7b,0xbf7fbe953f6d0000,0xbf62bf463f7b3f0e,0x3f22bef1bec43f35,0x3f753dc9bf553e48,
0x3f7f3e95bf6d8000,0x3f623f46bf7bbf0e,0xbf223ef13ec4bf35,0xbf75bdc93f55be48,0xbdc9bf753ec43f80,0x3ef1bf22be483f55,0x3f463f62bf6dbf35,0x3e953f7fbf0ebf7b,
0x3f58be89bf223f0e,0x3f7f3eb8bf78bd49,0xbf80bea13f750000,0xbf4abf513f713f18,0xbe2fbf7e3ef13f7b,0x3ee6bf39be163f67,0xbecf3f423dc9bf6d,0xbf5f3e603f2cbf04,
0x3f093f77bf46bf55,0xbd973f6fbe79bf80,0x3cc9bf733e953f80,0x3f1dbf13beac3f4e,0x3f7c3dfbbf623e48,0x3f653f31bf7dbedb,0xbf6abf273f7f3ec4,0xbefcbf7a3f3e3f5c,
0x3f183f67bf55bf35,0xbd493f78be95bf7f,0xbf5cbf2c3f7b3ec4,0xbeacbf7d3f223f62,0xbe163f71be48bf80,0xbf3e3f043ef1bf46,0xbe79bf803f0e3f6d,0x3edbbf4ebdc93f75,
0xbf4e3edb3f0ebf35,0xbf80be793f75bdc9,0x3f04bf3ebe483f6d,0x3f71be16bf463ef1,0xbf7dbeac3f7b8000,0xbf2cbf5c3f623f22,0x3f78bd49bf553ec4,0x3f673f18bf7fbe95,
0xbf733e603f46bf0e,0xbf6abefc3f803e16,0x3f7ebcc9bf623ec4,0x3f513f27bf78beac,0xbf7fbe2f3f75be48,0xbf31bf4a3f673f04,0x3f773eb8bf7f0000,0x3f093f65bf4ebf2c,
0xbea1bf7a3f223f55,0x3ecfbf5fbd493f7d,0x3dfb3f80bef1bf6d,0xbf133f423e79bf71,0x3d97bf7c3e953f7b,0x3f39bf1dbedb3f5c,0xbe893f6fbdc9bf80,0xbf583ee63f18bf3e,
0x3ec4bf6d00003f80,0x3f6dbec4bf353f35,0xbec43f6d0000bf80,0xbf6d3ec43f35bf35,0x3ec4bf6d00003f80,0x3f6dbec4bf353f35,0xbec43f6d0000bf80,0xbf6d3ec43f35bf35,
0x3f6d3ec4bf808000,0x3ec43f6dbf35bf35,0xbf6dbec43f808000,0xbec4bf6d3f353f35,0x3f6d3ec4bf808000,0x3ec43f6dbf35bf35,0xbf6dbec43f808000,0xbec4bf6d3f353f35,
0x3f423f13bf75be48,0x3cc93f7ebedbbf5c,0xbf5fbecf3f7f0000,0xbe60bf733f183f3e,0x3ee63f58bf46bf0e,0xbeb83f77bd49bf7d,0xbf1dbf393f623ec4,0x3e2fbf7f3e793f71,
0xbf273f513e95bf7b,0xbf803dfb3f67bf04,0x3efcbf6abdc93f80,0x3f7abea1bf4e3f2c,0xbf653f093f22bf55,0xbf6fbe893f80be16,0x3f4abf31bef13f6d,0x3f7c3d97bf783eac,
0xbf7d3eac3f55bf35,0xbf3ebf043f753dc9,0x3f783d49bf7b3ec4,0x3edb3f4ebf46bef1,0xbf183f673e48bf80,0xbf803e793f62bf22,0x3f5cbf2cbf0e3f6d,0x3f713e16bf7f3e95,
0xbe16bf713f0e3f35,0x3f2cbf5cbe953f7f,0xbe793f80be48bf6d,0xbf673f183f22bf62,0xbf4ebedb3f7b8000,0xbd49bf783ef13f46,0x3f043f3ebf55bec4,0xbeac3f7dbdc9bf75,
0x3f51bf4abef13f7b,0x3f733cc9bf7d3edb,0xbeb83f7fbdc9bf6d,0xbf773f093f3ebf5c,0xbe60bf5f3f223f0e,0x3f27bf6abe793f80,0x3f393ee6bf750000,0xbdfb3f7cbeacbf4e,
0x3f133f1dbf62be48,0xbea13f80be16bf67,0xbf6fbd973f7fbec4,0xbe89bf583f2c3f04,0x3f7abefcbf463f55,0x3f423ecfbf783d49,0xbf313f653e95bf80,0xbf7e3e2f3f71bf18,
0x3f46bf62bec43f80,0x3f75bdc9bf7b3f0e,0xbf7f3e953f6dbf35,0xbef1bf223f553e48,0x3f223ef1bf6d0000,0xbe953f7fbe48bf55,0x3dc9bf753ec43f35,0x3f62bf46bf0e3f7b,
0x3f223ef1bf6d8000,0xbe953f7fbe48bf55,0x3dc9bf753ec43f35,0x3f62bf46bf0e3f7b,0xbf463f623ec4bf80,0xbf753dc93f7bbf0e,0x3f7fbe95bf6d3f35,0x3ef13f22bf55be48,
0xbecf3f7fbdc9bf55,0xbf7e3f133f4ebf67,0xbf09befc3f620000,0x3ee6bf803d493f5c,0xbf31bea13f75be48,0x3e89bf7a3e793f3e,0x3f7cbf1dbf463f6d,0x3f273eb8bf713e16,
0xbf6a3d973f7fbf0e,0xbdfbbf513f183edb,0x3f58bf5fbef13f80,0x3f65bcc9bf803f04,0x3f39bf73be953f7b,0x3f77be60bf783f2c,0x3e2f3f4abf22bec4,0xbf423f6f3eacbf7d,
0x3eacbf783e483f35,0x3f7dbf2cbf463f75,0xbf803f183f55bf6d,0xbf04bedb3f62bdc9,0xbf673f5c3f0ebf80,0xbf4ebd493f7fbef1,0x3f3e3e16bf7b3ec4,0xbe793f71be95bf22,
0x3f71be79bf7b3f35,0x3e163f3ebf22be95,0xbd49bf4e3f0e3ec4,0x3f5cbf67bef13f7f,0xbedbbf043f558000,0x3f18bf80bdc93f62,0xbf2c3f7d3e48bf6d,0xbf783eac3f75bf46,
0xbf1d3f803dc9bf55,0xbf7a3ee63f71bf5c,0xbf27be2f3f75bec4,0x3ecfbf773e163f2c,0x3f5fbf6fbef13f7b,0x3f51bd97bf803f18,0x3ea13f09bf460000,0xbf393f7e3e79bf67,
0xbf4a3cc93f7fbf0e,0x3e60bf653eac3f04,0x3f42bf7cbe953f6d,0x3f6abe89bf7d3f3e,0x3efc3eb8bf623e48,0xbf133f7f3d49bf4e,0xbf733f583f22bf80,0xbf31bdfb3f78bedb,
0x3f7bbf55bf353f80,0x3f0e3e48bf6d3ec4,0xbe48bf0e3f350000,0x3f55bf7bbec43f6d,0xbf7b3f553f35bf80,0xbf0ebe483f6dbec4,0x3e483f0ebf350000,0xbf553f7b3ec4bf6d,
0x3e483f0ebf358000,0xbf553f7b3ec4bf6d,0x3f7bbf55bf353f80,0x3f0e3e48bf6d3ec4,0xbe48bf0e3f358000,0x3f55bf7bbec43f6d,0xbf7b3f553f35bf80,0xbf0ebe483f6dbec4,
0xbf7e3f313f62bf7b,0xbe60bee63f3ebe16,0xbd97bf133f220000,0x3f6abf77bf043f71,0x3f5fbeb8bf7f3f55,0xbe2f3f42bedbbe79,0xbea13f58be95bec4,0xbf803f4a3f4ebf80,
0x3dfbbf393ef13e48,0x3f7abf65bf2c3f7d,0x3f7fbf51bf463f80,0x3ecf3e89bf5c3eac,0xbefc3f6fbdc9bf0e,0xbf7c3f273f67bf78,0xbf733f093f75bf6d,0xbcc9bf1d3f183d49,
0x3f2cbe16bf7b3f35,0xbf043f67bdc9bef1,0x3f71bf78bf0e3f6d,0x3f18bd49bf753f22,0xbf803f4e3f55bf80,0xbe79beac3f46be95,0xbedb3f5cbe48bec4,0xbf7d3f3e3f62bf7f,
0xbf3e3f7d3e48bf35,0xbf5c3edb3f7fbf62,0x3eac3e79bf553ec4,0xbf4e3f803e95bf46,0x3d49bf183f0e8000,0x3f78bf71bf223f75,0xbf673f043f7bbf6d,0x3e16bf2c3ef13dc9,
0x3eb8bf423e953e48,0x3f7ebf51bf5c3f80,0x3f7abf77bf223f6d,0x3ee63cc9bf673f18,0x3f39bea1bf7f3f55,0xbefc3f58be16beac,0xbe2f3f1dbef10000,0xbf7f3f6a3f3ebf78,
0x3f6fbf27bf753f7b,0xbdfb3f13bf043d49,0x3e603e89bf463ec4,0xbf653f803edbbf4e,0xbf313f733dc9bf0e,0xbf5f3f093f7dbf71,0xbf7c3f4a3f62bf80,0xbd97becf3f2cbe79,
0x3f75bf46bf6d3f80,0xbdc93ef1bf0e3e48,0x3f62bf7fbec43f35,0x3f22be95bf7b3f55,0x3e95bf223ec40000,0x3f7fbf62bf553f7b,0xbef13dc93f6dbf35,0x3f46bf75be483f0e,
0xbe953f22bec48000,0xbf7f3f623f55bf7b,0x3ef1bdc9bf6d3f35,0xbf463f753e48bf0e,0x3f75bf46bf6d3f80,0xbdc93ef1bf0e3e48,0x3f62bf7fbec43f35,0x3f22be95bf7b3f55,
0xbe2fbdfb3f46bf0e,0x3f73bf80bf043f3e,0x3ecfbf273e950000,0x3f77bf58bf673f7d,0xbf7a3f5f3f62bf7b,0x3d97beb83f18beac,0xbf313ee63f7fbf6d,0x3f1dbf513d493e79,
0x3f7cbf7ebf223f55,0x3ea1bcc9bf5c3f2c,0x3f6abf42bf753f80,0xbe893f09bedb3e16,0x3e60befc3ef1be48,0x3f7fbf6fbf4e3f71,0x3f39bf65bdc93ec4,0x3f4abf13bf803f78,
0xbf783f803f0ebf35,0xbeac3e163f62bf46,0xbf4e3f673e48bec4,0xbf2c3f043f7fbf75,0xbf5c3f3e3f7bbf80,0x3edbbf183e95bdc9,0xbf7d3f713f55bf6d,0x3d49be793f22bef1,
0xbe793d493f55bf35,0x3f71bf7dbef13f22,0xbf183edb3f7bbf6d,0x3f3ebf5cbdc93e95,0x3f04bf2c3e488000,0x3f67bf4ebf753f7f,0x3e16beac3f0ebec4,0x3f80bf78bf463f62,
0xbd973e2fbf223f0e,0xbf803f7e3f3ebf4e,0xbe893eb8bef13ec4,0xbf7a3f733f5cbf67,0xbee63f09be953e48,0xbf6a3f5f3f71bf78,0xbf1d3f31bdc90000,0xbf513f423f7dbf80,
0xbf7f3f7c3f46bf55,0x3cc9bdfb3f2cbf18,0xbf773f6f3f62bf6d,0x3e60bea13f04bedb,0xbf653f583f75bf7b,0x3ecfbefc3eacbe79,0xbf4a3f393f7fbf80,0x3f13bf273e16bd49,
0xbf353f35bf803f80,0x3f35bf3500000000,0xbf353f35bf803f80,0x3f35bf3500000000,0xbf353f35bf803f80,0x3f35bf3500000000,0xbf353f35bf803f80,0x3f35bf3500000000,
0x3f35bf3580008000,0x3f35bf353f80bf80,0x3f35bf3580008000,0x3f35bf353f80bf80,0x3f35bf3580008000,0x3f35bf353f80bf80,0x3f35bf3580008000,0x3f35bf353f80bf80,
0xbf65bf583f623f55,0xbf6abf5f3f673f5c,0xbf4abf393f463f35,0xbf51bf423f4e3f3e,0xbf7fbf7c3f7f3f7b,0xbf80bf7e3f803f7d,0xbf77bf6f3f753f6d,0xbf7abf733f783f71,
0xbee6bf093ef13f0e,0xbecfbefc3edb3f04,0xbf1dbf313f223f35,0xbf13bf273f183f2c,0xbd97be2f3dc93e48,0xbcc9bdfb3d493e16,0xbe89beb83e953ec4,0xbe60bea13e793eac,
0xbf5cbf3e3f553f35,0xbf67bf4e3f623f46,0xbf7dbf713f7b3f6d,0xbf80bf783f7f3f75,0xbe79bd493e480000,0xbeacbe163e953dc9,0xbf18bedb3f0e3ec4,0xbf2cbf043f223ef1,
0xbf04bf2c3f0e3f35,0xbedbbf183ef13f22,0xbe16beac3e483ec4,0xbd49be793dc93e95,0xbf78bf803f7b3f80,0xbf71bf7d3f753f7f,0xbf4ebf673f553f6d,0xbf3ebf5c3f463f62,
0xbf7abf5f3f753f55,0xbf7fbf6f3f7d3f67,0xbf31bee63f223ec4,0xbf4abf133f3e3f04,0xbe2f3dfb3dc9be48,0xbea1bcc93e79bd49,0x3ecf3f27bef1bf35,0x3e893f09beacbf18,
0xbe60befc3e953f0e,0xbd97beb83e163edb,0xbf39bf653f463f6d,0xbf1dbf513f2c3f5c,0xbf7cbf7e3f7f3f7b,0xbf73bf803f783f80,0xbf6abf423f623f35,0xbf77bf583f713f4e,
0x3f623f7fbf6dbf80,0x3f463f75bf55bf7b,0x3e953f22bec4bf35,0x3dc93ef1be48bf0e,0xbef1bdc93ec40000,0xbf22be953f0e3e48,0xbf75bf463f6d3f35,0xbf7fbf623f7b3f55,
0xbef1bdc93ec48000,0xbf22be953f0e3e48,0xbf75bf463f6d3f35,0xbf7fbf623f7b3f55,0xbf62bf7f3f6d3f80,0xbf46bf753f553f7b,0xbe95bf223ec43f35,0xbdc9bef13e483f0e,
0x3f313f73bf46bf7b,0x3efc3f58bf18bf67,0x3f7c3f4abf75bf35,0x3f7f3f6abf80bf5c,0xbf6fbf273f623f0e,0xbf7ebf513f783f3e,0xbe603e893dc9bec4,0xbee63cc93eacbe16,
0xbf39bea13f223e48,0xbf5fbf093f4e3edb,0x3e2f3f1dbe95bf35,0xbd973ecfbd49bf04,0xbeb8bf423ef13f55,0xbdfbbf133e793f2c,0xbf7abf773f7f3f6d,0xbf65bf803f713f7d,
0x3d493f18be48bf35,0xbe793eac3dc9bef1,0xbf67bf043f553ec4,0xbf7dbf3e3f753f22,0x3f2c3e16bf0e0000,0x3f5c3edbbf46be95,0x3f713f78bf7bbf6d,0x3f4e3f80bf62bf7f,
0xbf80bf4e3f7b3f35,0xbf78bf713f7f3f62,0xbedbbf5c3f0e3f6d,0xbe16bf2c3e953f46,0x3f3e3f7dbf55bf80,0x3f043f67bf22bf75,0xbeac3e793e48bec4,0xbf18bd493ef1bdc9,
0xbf5fbeb83f463e48,0xbf7cbf273f713f04,0x3ea13f58bef1bf6d,0xbcc93f1dbe16bf3e,0x3f7e3f31bf75bf0e,0x3f7a3f65bf80bf4e,0x3d97bf133dc93f35,0x3ecfbe89be793edb,
0xbefcbf6f3f223f7b,0xbe2fbf423eac3f5c,0xbf73bf093f623ec4,0xbf80bf4a3f7d3f2c,0x3dfb3f39be95bf55,0xbe603ee63d49bf18,0x3f7f3f51bf7fbf35,0x3f6a3f77bf78bf67,
0xbf0ebf7b3f353f80,0xbe48bf553ec43f6d,0x3f553e48bf350000,0x3f7b3f0ebf6dbec4,0x3f0e3f7bbf35bf80,0x3e483f55bec4bf6d,0xbf55be483f350000,0xbf7bbf0e3f6d3ec4,
0x3f553e48bf358000,0x3f7b3f0ebf6dbec4,0x3f0e3f7bbf35bf80,0x3e483f55bec4bf6d,0xbf55be483f358000,0xbf7bbf0e3f6d3ec4,0xbf0ebf7b3f353f80,0xbe48bf553ec43f6d,
0x3efcbeb8be953f0e,0x3f513d97bf2c3e16,0xbf73bf583f7f3f35,0xbf39bf7e3f5c3f71,0xbf4abcc93f22be48,0xbf7abee63f673e79,0x3f423f7cbf62bf6d,0x3ecf3f77bf18bf80,
0x3f5f3f6fbf75bf55,0x3f133f7fbf3ebf7d,0x3ea1bf09bdc93f35,0x3f31bdfbbf043eac,0xbf1dbf803f463f7b,0xbe60bf653edb3f78,0xbf273e2f3ef1bec4,0xbf6abe893f4e3d49,
0x3f673f5cbf7bbf35,0x3f183f80bf46bf75,0xbf3e3e163f0ebec4,0xbf78beac3f623dc9,0xbf71be793f550000,0xbf7dbf2c3f7f3ef1,0x3d49bf4e3e483f6d,0x3f04bedbbe953f22,
0xbedb3f043e48bf35,0xbf4e3d493f22be95,0xbf2cbf7d3f553f6d,0xbe79bf713ef13f7f,0xbeacbf783f0e3f80,0x3e16bf3e3dc93f62,0x3f803f18bf7bbec4,0x3f5c3f67bf75bf46,
0xbf313ea13ef1bf0e,0xbf77be603f5cbd49,0x3f7c3f1dbf7fbec4,0x3f423f6fbf67bf4e,0xbecfbf7f3f223f7b,0x3dfbbf513e163f71,0xbf093efc3e95bf35,0xbf65bcc93f3ebe79,
0xbf39bf733f623f55,0xbe89bf7a3f043f80,0xbe2f3f4abdc9bf6d,0xbf273eb83edbbf18,0x3f6a3d97bf463e48,0x3f7e3f13bf7dbeac,0xbf58bf5f3f753f35,0xbee6bf803f2c3f78,
0x3dc93f75bec4bf80,0xbef13f223e48bf55,0xbf46bf623f6d3f35,0xbe95bf7f3f0e3f7b,0x3f7f3e95bf6d0000,0x3f623f46bf7bbf0e,0xbf223ef13ec4bf35,0xbf75bdc93f55be48,
0xbf7fbe953f6d8000,0xbf62bf463f7b3f0e,0x3f22bef1bec43f35,0x3f753dc9bf553e48,0x3dc93f75bec4bf80,0xbef13f223e48bf55,0xbf46bf623f6d3f35,0xbe95bf7f3f0e3f7b,
0xbf7abefc3f7f3e48,0xbf27bf6a3f5c3f3e,0x3f313f65bf62bf35,0x3dfb3f7cbedbbf7d,0xbf133f1d3e95bf55,0xbf733cc93f4ebeac,0x3f6fbd97bf463ec4,0x3f773f09bf80be79,
0x3e60bf5f3dc93f7b,0x3f42becfbf043f2c,0xbf393ee63ef1bf35,0xbf7ebe2f3f67be16,0xbf51bf4a3f753f0e,0xbea1bf803f183f71,0x3eb83f7fbf22bf6d,0xbe893f58bd49bf78,
0x3f4ebedbbf0e3f35,0x3f803e79bf753dc9,0xbf043f3e3e48bf6d,0xbf713e163f46bef1,0x3f7d3eacbf7b0000,0x3f2c3f5cbf62bf22,0xbf783d493f55bec4,0xbf67bf183f7f3e95,
0x3f183f67bf55bf35,0xbd493f78be95bf7f,0xbf5cbf2c3f7b3ec4,0xbeacbf7d3f223f62,0xbe163f71be48bf80,0xbf3e3f043ef1bf46,0xbe79bf803f0e3f6d,0x3edbbf4ebdc93f75,
0xbee63f583dc9bf7b,0xbf6f3e893f3ebf18,0x3f1dbf39be953f6d,0x3f7cbd97bf5c3edb,0xbf423f133ef1bf55,0xbf80bdfb3f71be79,0x3f5fbecfbf223f35,0x3f7a3ea1bf7d3d49,
0xbf65bf093f7f3e48,0xbeb8bf773f2c3f4e,0x3f4a3f31bf75bec4,0x3e2f3f7fbf04bf67,0xbf27bf513f623f0e,0x3cc9bf7e3eac3f78,0x3efc3f6abf46bf35,0xbe603f73be16bf80,
0x3ec4bf6d00003f80,0x3f6dbec4bf353f35,0xbec43f6d0000bf80,0xbf6d3ec43f35bf35,0x3ec4bf6d00003f80,0x3f6dbec4bf353f35,0xbec43f6d0000bf80,0xbf6d3ec43f35bf35,
0x3f6d3ec4bf808000,0x3ec43f6dbf35bf35,0xbf6dbec43f808000,0xbec4bf6d3f353f35,0x3f6d3ec4bf808000,0x3ec43f6dbf35bf35,0xbf6dbec43f808000,0xbec4bf6d3f353f35,
0x3d973f7cbef1bf55,0xbf313f4a3eacbf78,0xbe89bf6f3f223f35,0x3f09bf65be163f80,0xbea13f7abdc9bf7b,0xbf6a3efc3f2cbf4e,0x3dfbbf803e953f6d,0x3f51bf27bf043f67,
0xbf7f3e2f3f62bf0e,0xbf39bf1d3f713e79,0x3f77beb8bf463f35,0x3f583ee6bf7dbd49,0xbf73be603f7fbe48,0xbecfbf5f3f3e3f18,0x3f7e3cc9bf753ec4,0x3f133f42bf5cbedb,
0xbe16bf713f0e3f35,0x3f2cbf5cbe953f7f,0xbe793f80be48bf6d,0xbf673f183f22bf62,0xbf4ebedb3f7b0000,0xbd49bf783ef13f46,0x3f043f3ebf55bec4,0xbeac3f7dbdc9bf75,
0x3f7dbeacbf553f35,0x3f3e3f04bf75bdc9,0xbf78bd493f7bbec4,0xbedbbf4e3f463ef1,0x3f18bf67be483f80,0x3f80be79bf623f22,0xbf5c3f2c3f0ebf6d,0xbf71be163f7fbe95,
0xbe2f3f7ebe95bf55,0xbf653f313f18bf71,0xbecfbf423f463ec4,0x3efcbf7abd493f78,0x3f583e89bf7f3e48,0x3d973f6fbf04bf2c,0xbf803ea13f62bf35,0xbf1dbf133f673e16,
0xbf7c3dfb3f75bf0e,0xbee6bf393f4e3eac,0x3f6abf27bf223f6d,0x3f5f3e60bf803e79,0xbf093f773dc9bf7b,0xbf7f3eb83f5cbf3e,0xbcc9bf733ef13f35,0x3f4abf51bedb3f7d,
0xbf463f623ec4bf80,0xbf753dc93f7bbf0e,0x3f7fbe95bf6d3f35,0x3ef13f22bf55be48,0xbf22bef13f6d0000,0x3e95bf7f3e483f55,0xbdc93f75bec4bf35,0xbf623f463f0ebf7b,
0xbf22bef13f6d8000,0x3e95bf7f3e483f55,0xbdc93f75bec4bf35,0xbf623f463f0ebf7b,0x3f46bf62bec43f80,0x3f75bdc9bf7b3f0e,0xbf7f3e953f6dbf35,0xbef1bf223f553e48,
0x3f6fbf42bf223f7b,0x3f4a3e2fbf7d3eac,0xbe603f77be95bf35,0xbf733f393f2cbf78,0xbcc93f65bef1bf0e,0xbf5f3f583f04bf80,0xbf51bdfb3f7fbec4,0x3d97bf6a3edb3f18,
0x3eb83f27bf46be48,0xbf1d3f7c3e16bf71,0xbf7a3e893f75bf35,0xbea1bf313f3e3e79,0xbf803ee63f62bf55,0xbefcbf093f5c3d49,0x3f13bf7ebdc93f6d,0x3f7fbecfbf673f4e,
0xbf713e793f7bbf35,0xbe16bf3e3f223e95,0x3d493f4ebf0ebec4,0xbf5c3f673ef1bf7f,0x3edb3f04bf550000,0xbf183f803dc9bf62,0x3f2cbf7dbe483f6d,0x3f78beacbf753f46,
0x3eacbf783e483f35,0x3f7dbf2cbf463f75,0xbf803f183f55bf6d,0xbf04bedb3f62bdc9,0xbf673f5c3f0ebf80,0xbf4ebd493f7fbef1,0x3f3e3e16bf7b3ec4,0xbe793f71be95bf22,
0x3dfb3f31bf22be48,0xbf583f733edbbf78,0xbf7f3f133f62bf6d,0xbeb8befc3f4ebd49,0x3e89bf6a3e953f0e,0x3f7cbf42bf3e3f7d,0x3f65be60bf7f3f35,0xbcc93f4abf04beac,
0xbf7e3f393f46bf7b,0xbf09bea13f67be79,0x3d97bf513ef13ec4,0x3f6fbf5fbf183f80,0x3f77becfbf753f55,0x3e2f3f27bf2cbe16,0xbee63f7abdc9bf35,0xbf803f1d3f5cbf71,
0x3f7bbf55bf353f80,0x3f0e3e48bf6d3ec4,0xbe48bf0e3f350000,0x3f55bf7bbec43f6d,0xbf7b3f553f35bf80,0xbf0ebe483f6dbec4,0x3e483f0ebf350000,0xbf553f7b3ec4bf6d,
0x3e483f0ebf358000,0xbf553f7b3ec4bf6d,0x3f7bbf55bf353f80,0x3f0e3e48bf6d3ec4,0xbe48bf0e3f358000,0x3f55bf7bbec43f6d,0xbf7b3f553f35bf80,0xbf0ebe483f6dbec4,
0xbf1dbcc93f75bf0e,0x3f09bf733d493f18,0x3f27bf7cbdc93f35,0x3f6fbefcbf783f67,0x3e893ecfbf463e48,0xbf513f7f3eacbf5c,0xbf653f7a3ef1bf6d,0xbf393dfb3f7dbf2c,
0x3f4abf80be953f55,0x3f58bea1bf803f4e,0x3f42be2fbf7f3f35,0xbeb83f5fbe79bedb,0xbf773f6a3f22bf7b,0xbf13bd973f71bf04,0xbee6be603f62bec4,0x3f31bf7ebe163f3e,
0xbf3e3f7d3e48bf35,0xbf5c3edb3f7fbf62,0x3eac3e79bf553ec4,0xbf4e3f803e95bf46,0x3d49bf183f0e0000,0x3f78bf71bf223f75,0xbf673f043f7bbf6d,0x3e16bf2c3ef13dc9,
0xbf2c3e163f7bbf35,0x3f04bf673dc93ef1,0xbf713f783f0ebf6d,0xbf183d493f75bf22,0x3f80bf4ebf553f80,0x3e793eacbf463e95,0x3edbbf5c3e483ec4,0x3f7dbf3ebf623f7f,
0x3ecf3d97bf623f0e,0xbf4a3f7c3e79bf2c,0xbf093f5fbdc9bec4,0xbf733f313f71bf7d,0xbf803f653f46bf7b,0xbe89be603f4ebedb,0xbf133dfb3f75bf35,0x3f27bf6fbd493f04,
0xbf6a3f7f3ef1bf55,0xbf1d3e2f3f78bf3e,0xbf583efc3f7fbf6d,0x3ea1bf393eac3e16,0xbcc9bee63f22be48,0x3f77bf7abf183f67,0x3f51bf7ebe953f35,0x3f42beb8bf803f5c,
0xbf753f463f6dbf80,0x3dc9bef13f0ebe48,0xbf623f7f3ec4bf35,0xbf223e953f7bbf55,0xbe953f22bec40000,0xbf7f3f623f55bf7b,0x3ef1bdc9bf6d3f35,0xbf463f753e48bf0e,
0x3e95bf223ec48000,0x3f7fbf62bf553f7b,0xbef13dc93f6dbf35,0x3f46bf75be483f0e,0xbf753f463f6dbf80,0x3dc9bef13f0ebe48,0xbf623f7f3ec4bf35,0xbf223e953f7bbf55,
0xbf133f4abdc9be48,0xbf653f393f78bf80,0xbf6f3f7f3ef1bf35,0xbefc3e603f71bf4e,0x3f09be89bf753f55,0xbf423f6a3e16bedb,0xbcc93ea1bf223ec4,0xbf7e3f7c3f2cbf5c,
0xbf513f1d3f7fbf7b,0x3ee6bf313e793d49,0xbeb83d973f62bf35,0x3f5fbf7abeac3f18,0xbf583f773e95bf0e,0xbf273ecf3f7dbf67,0xbf803f733f46bf6d,0xbdfbbe2f3f3ebf04,
0x3e79bd49bf553f35,0xbf713f7d3ef1bf22,0x3f18bedbbf7b3f6d,0xbf3e3f5c3dc9be95,0xbf043f2cbe480000,0xbf673f4e3f75bf7f,0xbe163eacbf0e3ec4,0xbf803f783f46bf62,
0xbf783f803f0ebf35,0xbeac3e163f62bf46,0xbf4e3f673e48bec4,0xbf2c3f043f7fbf75,0xbf5c3f3e3f7bbf80,0x3edbbf183e95bdc9,0xbf7d3f713f55bf6d,0x3d49be793f22bef1,
0x3f27bf13bf7f3f7b,0xbf393f4a3d49be16,0x3efcbecfbf753f6d,0xbf583f653e79beac,0x3ea1be60bf623f55,0xbf6f3f773edbbf04,0x3dfbbcc9bf463f35,0xbf7c3f7f3f18bf2c,
0xbf423f513dc9be48,0xbf313f1d3f80bf7d,0xbf5f3f6a3e95bec4,0xbf093ee63f78bf71,0xbf733f7a3ef1bf0e,0xbeb83e893f67bf5c,0xbf7e3f803f22bf35,0xbe2f3d973f4ebf3e,
0x3f35bf35bf803f80,0xbf353f3500000000,0x3f35bf35bf803f80,0xbf353f3500000000,0x3f35bf35bf803f80,0xbf353f3500000000,0x3f35bf35bf803f80,0xbf353f3500000000,
0x3f35bf3580008000,0x3f35bf35bf803f80,0x3f35bf3580008000,0x3f35bf35bf803f80,0x3f35bf3580008000,0x3f35bf35bf803f80,0x3f35bf3580008000,0x3f35bf35bf803f80,
0x3ea13e603f753f7b,0xbeb8be89bf71bf78,0x3dfb3cc93f7f3f80,0xbe2fbd97bf7dbf80,0x3f273f133f463f55,0xbf31bf1dbf3ebf4e,0x3efc3ecf3f623f6d,0xbf09bee6bf5cbf67,
0x3f733f7abe95be48,0xbf6fbf773eac3e79,0x3f7e3f80bdc98000,0xbf7cbf7f3e163d49,0x3f423f51bf22bf0e,0xbf39bf4a3f2c3f18,0x3f5f3f6abef1bec4,0xbf58bf653f043edb,
0x3f5c3f3e3f0e3f35,0xbf67bf4ebef1bf22,0x3f7d3f713e483ec4,0xbf80bf78bdc9be95,0x3e793d493f7b3f80,0xbeacbe16bf75bf7f,0x3f183edb3f553f6d,0xbf2cbf04bf46bf62,
0x3f043f2cbf55bf35,0xbedbbf183f623f46,0x3e163eacbf7bbf6d,0xbd49be793f7f3f75,0x3f783f80be488000,0xbf71bf7d3e953dc9,0x3f4e3f67bf0ebec4,0xbf3ebf5c3f223ef1,
0x3f583f77bef1be48,0xbf42bf6a3f183eac,0x3f803f733dc93ec4,0xbf7ebf7c3d49be79,0x3f513f1d3f223f55,0xbf65bf39bf04bf3e,0x3eb83d973f753f80,0xbefcbe60bf67bf7d,
0xbf09be89bf62bf7b,0x3f273ecf3f4e3f71,0x3cc93ea1bf7fbf6d,0x3dfbbe2f3f803f78,0x3f133f4abf46bf0e,0xbee6bf313f5c3f2c,0x3f6f3f7fbe958000,0xbf5fbf7a3edb3e16,
0x3ef13dc93f6d3f80,0xbf22be95bf55bf7b,0x3f753f463ec43f35,0xbf7fbf62be48bf0e,0x3f623f7fbec40000,0xbf46bf753f0e3e48,0x3e953f22bf6dbf35,0xbdc9bef13f7b3f55,
0x3f623f7fbec48000,0xbf46bf753f0e3e48,0x3e953f22bf6dbf35,0xbdc9bef13f7b3f55,0xbef1bdc9bf6dbf80,0x3f223e953f553f7b,0xbf75bf46bec4bf35,0x3f7f3f623e483f0e,
0x3f803f653dc93f0e,0xbf77bf7a3e16beac,0x3f133dfb3f623f80,0xbf42beb8bf3ebf78,0xbecf3d97bf75bf7b,0x3f1d3e2f3f5c3f80,0x3f093f5fbf46bec4,0xbea1bf393f673f18,
0xbcc93ee6bf7fbf55,0x3e89be603f7d3f71,0x3f513f7ebef18000,0xbf27bf6f3f2c3e79,0xbf6abf7f3e95be48,0x3f4a3f7cbf04bd49,0xbf58befcbf22bf6d,0x3f733f313edb3f4e,
0x3d493f18bf7bbf35,0x3e79beac3f7f3f62,0xbf67bf04bf0ebf6d,0x3f7d3f3e3e953f46,0x3f2c3e163f553f80,0xbf5cbedbbf22bf75,0x3f713f78be483ec4,0xbf4ebf803ef1bdc9,
0xbf80bf4ebe48bf35,0x3f783f71bdc93ef1,0xbedbbf5c3f553ec4,0x3e163f2cbf75bf22,0x3f3e3f7dbf0e8000,0xbf04bf673f463e95,0xbeac3e79bf7bbf6d,0x3f183d493f623f7f,
0xbf77bf6a3dc9bf0e,0x3f513f7fbedb3e79,0xbee63e60bf75bf6d,0x3f393dfb3f4e3f80,0x3f4a3f80bef13e48,0xbf09bf733f3e3e16,0x3f423e2f3f463f80,0xbf6fbefcbf04bf71,
0x3e89becf3f7f3f55,0xbf133d97bf67bf78,0xbf65bf7a3e95bec4,0x3f313f7ebf183d49,0xbf1d3cc9bf62bf7b,0x3f583ea13f2c3f7d,0x3f273f7cbf228000,0xbeb8bf5f3f5c3eac,
0x3f553e483f353f80,0xbf7bbf0ebec4bf6d,0x3f0e3f7bbf350000,0xbe48bf553f6d3ec4,0xbf55be48bf35bf80,0x3f7b3f0e3ec43f6d,0xbf0ebf7b3f350000,0x3e483f55bf6dbec4,
0x3f0e3f7bbf358000,0xbe48bf553f6d3ec4,0xbf55be48bf35bf80,0x3f7b3f0e3ec43f6d,0xbf0ebf7b3f358000,0x3e483f55bf6dbec4,0x3f553e483f353f80,0xbf7bbf0ebec4bf6d,
0x3e893f6abf62be48,0x3e2fbf273f803f18,0x3f653e603f223f80,0xbf80bf1dbe79bf67,0x3dfbbf313f7f3f0e,0xbf093ea1bf71bf5c,0xbf7fbf13be95bf6d,0x3f6f3f5fbe163f2c,
0xbf77becfbef1bf7b,0x3f7c3f423d493f4e,0x3ee63f7abf468000,0xbcc9bf4a3f783edb,0x3f7e3f393dc93f55,0xbf58bf733eacbf04,0xbd97bf513f753ec4,0xbeb83efcbf7dbf3e,
0xbf67bf5c3e48bf35,0x3f183f80bf223e95,0x3f3ebe163f553f6d,0xbf78beacbef1bf7f,0x3f713e793f0e3f80,0xbf7dbf2cbdc9bf62,0xbd493f4ebf7bbec4,0x3f04bedb3f753f46,
0x3edbbf043f7b3f35,0xbf4e3d49bf46bf75,0x3f2c3f7dbf0e3ec4,0xbe79bf713f623dc9,0x3eac3f78bf558000,0x3e16bf3e3f7f3ef1,0xbf80bf18be48bf6d,0x3f5c3f67be953f22,
0x3f803ee63e953f7b,0xbf5fbf583e79bf3e,0xbf13bf7e3f22bec4,0x3d973f6abf71be16,0xbeb83f27bf7fbf0e,0x3f4abe2f3f4e3f67,0x3f7a3e893ef13f80,0xbf73bf393d49bf5c,
0x3cc93f65bf75be48,0x3efcbf093f783f2c,0x3f51bdfb3f463f6d,0xbf7fbecfbeacbf7d,0xbf6fbf423dc9bf55,0x3f1d3f7cbf183edb,0x3e603f77bf628000,0x3ea1bf313f803f04,
0x3f7f3e953ec43f80,0xbf62bf463e48bf55,0xbf223ef1bf6dbf35,0x3f753dc93f0e3f7b,0xbdc9bf753f6d0000,0xbef13f22bf7bbf0e,0x3f463f62bec43f35,0xbe95bf7f3f55be48,
0x3dc93f75bf6d8000,0x3ef1bf223f7b3f0e,0xbf46bf623ec4bf35,0x3e953f7fbf553e48,0x3f7f3e953ec43f80,0xbf62bf463e48bf55,0xbf223ef1bf6dbf35,0x3f753dc93f0e3f7b,
0xbf583e89bf46bf55,0x3f7f3eb83e793f80,0x3f803ea13e953f80,0xbf4abf513eacbf4e,0x3e2f3f7ebf623e48,0x3ee6bf393f7d3edb,0x3ecfbf423f7f3ec4,0xbf5f3e60bf3ebf5c,
0xbf09bf773f22bf0e,0xbd973f6fbf78bd49,0xbcc93f73bf758000,0x3f1dbf133f713f18,0xbf7cbdfbbef1bf7b,0x3f653f31be163f67,0x3f6a3f27bdc93f6d,0xbefcbf7a3f2cbf04,
0x3f4ebedb3f553f35,0xbf80be79be95bf7f,0xbf043f3ebf7bbec4,0x3f71be163f223f62,0x3f7d3eac3e483f80,0xbf2cbf5c3ef1bf46,0xbf783d49bf0ebf6d,0x3f673f18bdc93f75,
0x3f183f67bf0e3f35,0x3d49bf783f75bdc9,0xbf5cbf2c3e48bf6d,0x3eac3f7dbf463ef1,0xbe163f71bf7b8000,0x3f3ebf043f623f22,0xbe79bf803f55bec4,0xbedb3f4ebf7fbe95,
0xbf733e60bf22bf55,0x3f6a3efcbd493f7d,0x3f7ebcc93ef13f6d,0xbf51bf273e79bf71,0xbf7fbe2fbe95bf7b,0x3f313f4abedb3f5c,0x3f773eb83dc93f80,0xbf09bf653f18bf3e,
0xbea1bf7a3f46bf0e,0xbecf3f5fbf80be16,0x3dfb3f80bf623ec4,0x3f13bf423f783eac,0x3d97bf7c3f75be48,0xbf393f1dbf67bf04,0xbe893f6fbf7f8000,0x3f58bee63f4e3f2c,
0x3f6d3ec400003f80,0xbec4bf6d3f35bf35,0xbf6dbec40000bf80,0x3ec43f6dbf353f35,0x3f6d3ec400003f80,0xbec4bf6d3f35bf35,0xbf6dbec40000bf80,0x3ec43f6dbf353f35,
0xbec43f6dbf808000,0x3f6dbec43f353f35,0x3ec4bf6d3f808000,0xbf6d3ec4bf35bf35,0xbec43f6dbf808000,0x3f6dbec43f353f35,0x3ec4bf6d3f808000,0xbf6d3ec4bf35bf35,
0xbf42bf133e95bf7b,0x3cc93f7ebf673f04,0x3f5f3ecfbdc93f80,0xbe60bf733f4ebf2c,0xbee6bf583f22bf55,0xbeb83f77bf803e16,0x3f1d3f39bef13f6d,0x3e2fbf7f3f78beac,
0x3f27bf513f753e48,0xbf803dfbbedbbf5c,0xbefc3f6abf7f8000,0x3f7abea13f183f3e,0x3f65bf093f463f0e,0xbf6fbe89bd49bf7d,0xbf4a3f31bf62bec4,0x3f7c3d973e793f71,
0x3e163f71bf553f35,0x3f2cbf5c3f753dc9,0x3e79bf803f7bbec4,0xbf673f18bf46bef1,0x3f4e3edbbe483f80,0xbd49bf783f62bf22,0xbf04bf3e3f0ebf6d,0xbeac3f7dbf7f3e95,
0xbf7d3eacbf0ebf35,0x3f3e3f04be953f7f,0x3f783d493e483f6d,0xbedbbf4e3f22bf62,0xbf183f67bf7b8000,0x3f80be793ef13f46,0x3f5cbf2c3f553ec4,0xbf71be16bdc9bf75,
0x3f51bf4a3f623e48,0xbf73bcc9be16bf67,0xbeb83f7fbf7f3ec4,0x3f77bf093f2c3f04,0xbe60bf5f3f46bf55,0xbf273f6abf783d49,0x3f393ee6be953f80,0x3dfbbf7c3f71bf18,
0x3f133f1dbef13f7b,0x3ea1bf803f7dbedb,0xbf6fbd97bdc9bf6d,0x3e893f58bf3e3f5c,0x3f7abefc3f223f0e,0xbf42becf3e79bf80,0xbf313f65bf758000,0x3f7ebe2f3eac3f4e,
0x3f223ef1bec43f80,0x3e95bf7f3f7bbf0e,0x3dc9bf753f6dbf35,0xbf623f46bf55be48,0xbf463f62bf6d0000,0x3f75bdc93e483f55,0x3f7fbe953ec43f35,0xbef1bf223f0ebf7b,
0xbf463f62bf6d8000,0x3f75bdc93e483f55,0x3f7fbe953ec43f35,0xbef1bf223f0ebf7b,0xbf22bef13ec4bf80,0xbe953f7fbf7b3f0e,0xbdc93f75bf6d3f35,0x3f62bf463f553e48,
0x3ecfbf7f3f7fbf0e,0xbf7e3f13bf18bedb,0x3f093efcbef13f80,0x3ee6bf803f80bf04,0x3f313ea1be953f7b,0x3e89bf7a3f78bf2c,0xbf7c3f1dbf22bec4,0x3f273eb8beac3f7d,
0x3f6abd973dc93f55,0xbdfbbf513f4ebf67,0xbf583f5fbf628000,0x3f65bcc93d493f5c,0xbf393f73bf753e48,0x3f77be603e793f3e,0xbe2fbf4a3f46bf6d,0xbf423f6fbf713e16,
0xbf713e79be48bf35,0x3e163f3ebf463f75,0x3d493f4ebf553f6d,0x3f5cbf673f62bdc9,0x3edb3f04bf0e3f80,0x3f18bf803f7fbef1,0x3f2cbf7d3f7bbec4,0xbf783eacbe95bf22,
0x3eacbf783f7bbf35,0xbf7d3f2cbf22be95,0xbf803f18bf0ebec4,0x3f043edbbef13f7f,0xbf673f5cbf558000,0x3f4e3d49bdc93f62,0x3f3e3e16be483f6d,0x3e79bf713f75bf46,
0xbf1d3f80bf7f3f0e,0x3f7abee63eac3f04,0xbf27be2f3e95bf6d,0xbecf3f77bf7d3f3e,0x3f5fbf6f3f62be48,0xbf513d973d49bf4e,0x3ea13f09bf223f80,0x3f39bf7e3f78bedb,
0xbf4a3cc93dc9bf55,0xbe603f65bf713f5c,0x3f42bf7c3f75bec4,0xbf6a3e89be16bf2c,0x3efc3eb8bef13f7b,0x3f13bf7f3f80bf18,0xbf733f58bf468000,0x3f313dfbbe793f67,
0x3e483f0ebf353f80,0x3f55bf7b3f6dbec4,0x3f7bbf553f350000,0xbf0ebe483ec4bf6d,0xbe48bf0e3f35bf80,0xbf553f7bbf6d3ec4,0xbf7b3f55bf350000,0x3f0e3e48bec43f6d,
0xbf7b3f55bf358000,0x3f0e3e48bec43f6d,0x3e483f0ebf353f80,0x3f55bf7b3f6dbec4,0x3f7bbf553f358000,0xbf0ebe483ec4bf6d,0xbe48bf0e3f35bf80,0xbf553f7bbf6d3ec4,
0x3f7ebf313ef13e48,0xbe60bee63f2cbf7d,0x3d973f13bf463f80,0x3f6abf773f5cbeac,0xbf5f3eb8bdc9bf0e,0xbe2f3f42bf673f78,0x3ea1bf583f75bf6d,0xbf803f4abf18bd49,
0xbdfb3f39bf623f7b,0x3f7abf653f3ebe16,0xbf7f3f51bf228000,0x3ecf3e89bf043f71,0x3efcbf6f3f7fbf55,0xbf7c3f27bedbbe79,0x3f73bf093e953ec4,0xbcc9bf1d3f4ebf80,
0x3f3ebf7d3f7bbf35,0xbf5c3edbbdc9bef1,0xbeacbe793f0ebf6d,0xbf4e3f80bf753f22,0xbd493f18bf553f80,0x3f78bf713f46be95,0x3f67bf043e483ec4,0x3e16bf2c3f62bf7f,
0x3f2cbe16be483f35,0x3f04bf673f7fbf62,0x3f71bf783f55bec4,0xbf183d493e95bf46,0xbf803f4ebf0e8000,0x3e793eacbf223f75,0xbedb3f5cbf7b3f6d,0x3f7dbf3e3ef13dc9,
0x3eb8bf423f75bf7b,0xbf7e3f51bf043d49,0x3f7abf773f46bec4,0xbee6bcc93edbbf4e,0x3f39bea1bdc93f0e,0x3efcbf583f7dbf71,0xbe2f3f1dbf623f80,0x3f7fbf6a3f2cbe79,
0x3f6fbf273e953e48,0x3dfbbf133f5cbf80,0x3e603e89bf223f6d,0x3f65bf803f67bf18,0xbf313f73bf7f3f55,0x3f5fbf093e163eac,0xbf7c3f4abef18000,0x3d973ecfbf3e3f78,
0xbe953f22bf6d3f80,0x3f7fbf623f0ebe48,0x3ef1bdc9bec43f35,0x3f46bf753f7bbf55,0x3f75bf463ec40000,0x3dc9bef13f55bf7b,0x3f62bf7f3f6dbf35,0xbf223e953e48bf0e,
0xbf753f46bec48000,0xbdc93ef1bf553f7b,0xbf623f7fbf6d3f35,0x3f22be95be483f0e,0xbe953f22bf6d3f80,0x3f7fbf623f0ebe48,0x3ef1bdc9bec43f35,0x3f46bf753f7bbf55,
0x3e2f3dfbbf223f55,0x3f73bf803f5cbf2c,0xbecf3f27bf753f80,0x3f77bf583edbbe16,0x3f7abf5f3ef1be48,0x3d97beb83f4ebf71,0x3f31bee6bdc93ec4,0x3f1dbf513f80bf78,
0xbf7c3f7ebf463f0e,0x3ea1bcc9bf043f3e,0xbf6a3f42be958000,0xbe893f09bf673f7d,0xbe603efcbf623f7b,0x3f7fbf6f3f18beac,0xbf393f65bf7f3f6d,0x3f4abf133d493e79,
0x3e79bd49bf0e3f35,0x3f71bf7d3f62bf46,0x3f18bedbbe483ec4,0x3f3ebf5c3f7fbf75,0xbf043f2cbf7b3f80,0x3f67bf4e3e95bdc9,0xbe163eacbf553f6d,0x3f80bf783f22bef1,
0xbf783f80bf553f35,0x3eacbe16bef13f22,0xbf4e3f67bf7b3f6d,0x3f2cbf04bdc93e95,0xbf5c3f3ebe488000,0xbedb3f18bf753f7f,0xbf7d3f71bf0e3ec4,0xbd493e79bf463f62,
0xbd973e2fbf463f55,0x3f80bf7e3f2cbf18,0xbe893eb8bf623f6d,0x3f7abf733f04bedb,0xbee63f09bf753f7b,0x3f6abf5f3eacbe79,0xbf1d3f31bf7f3f80,0x3f51bf423e16bd49,
0xbf7f3f7cbf223f0e,0xbcc93dfbbf3e3f4e,0xbf773f6fbef13ec4,0xbe603ea1bf5c3f67,0xbf653f58be953e48,0xbecf3efcbf713f78,0xbf4a3f39bdc98000,0xbf133f27bf7d3f80,
0x3f35bf35bf803f80,0xbf353f3500000000,0x3f35bf35bf803f80,0xbf353f3500000000,0x3f35bf35bf803f80,0xbf353f3500000000,0x3f35bf35bf803f80,0xbf353f3500000000,
0x3f35bf3580008000,0x3f35bf35bf803f80,0x3f35bf3580008000,0x3f35bf35bf803f80,0x3f35bf3580008000,0x3f35bf35bf803f80,0x3f35bf3580008000,0x3f35bf35bf803f80,
0x3f653f583ef13f0e,0xbf6abf5fbedbbf04,0x3f4a3f393f223f35,0xbf51bf42bf18bf2c,0x3f7f3f7c3dc93e48,0xbf80bf7ebd49be16,0x3f773f6f3e953ec4,0xbf7abf73be79beac,
0x3ee63f09bf62bf55,0xbecfbefc3f673f5c,0x3f1d3f31bf46bf35,0xbf13bf273f4e3f3e,0x3d973e2fbf7fbf7b,0xbcc9bdfb3f803f7d,0x3e893eb8bf75bf6d,0xbe60bea13f783f71,
0x3f043f2cbf55bf35,0xbedbbf183f623f46,0x3e163eacbf7bbf6d,0xbd49be793f7f3f75,0x3f783f80be480000,0xbf71bf7d3e953dc9,0x3f4e3f67bf0ebec4,0xbf3ebf5c3f223ef1,
0xbf5cbf3ebf0ebf35,0x3f673f4e3ef13f22,0xbf7dbf71be48bec4,0x3f803f783dc93e95,0xbe79bd49bf7bbf80,0x3eac3e163f753f7f,0xbf18bedbbf55bf6d,0x3f2c3f043f463f62,
0xbf7abf5fbe95bf0e,0x3f7f3f6f3e163edb,0xbf31bee6bf46bf6d,0x3f4a3f133f2c3f5c,0xbe2f3dfbbf7fbf7b,0x3ea13cc93f783f80,0x3ecf3f27bf62bf35,0xbe89bf093f713f4e,
0xbe60befc3f753f55,0x3d973eb8bf7dbf67,0xbf39bf653f223ec4,0x3f1d3f51bf3ebf04,0xbf7cbf7e3dc9be48,0x3f733f80be793d49,0xbf6abf42bef1bf35,0x3f773f583eac3f18,
0xbef1bdc9bf6dbf80,0x3f223e953f553f7b,0xbf75bf46bec4bf35,0x3f7f3f623e483f0e,0xbf62bf7f3ec40000,0x3f463f75bf0ebe48,0xbe95bf223f6d3f35,0x3dc93ef1bf7bbf55,
0xbf62bf7f3ec48000,0x3f463f75bf0ebe48,0xbe95bf223f6d3f35,0x3dc93ef1bf7bbf55,0x3ef13dc93f6d3f80,0xbf22be95bf55bf7b,0x3f753f463ec43f35,0xbf7fbf62be48bf0e,
0xbf31bf733f223e48,0x3efc3f58bf4ebedb,0xbf7cbf4abe95bf35,0x3f7f3f6a3d493f04,0x3f6f3f273ef13f55,0xbf7ebf51be79bf2c,0x3e60be893f7f3f6d,0xbee63cc9bf71bf7d,
0x3f393ea13f463f7b,0xbf5fbf09bf18bf67,0xbe2fbf1d3f753f35,0xbd973ecfbf80bf5c,0x3eb83f42bf62bf0e,0xbdfbbf133f783f3e,0x3f7a3f77bdc93ec4,0xbf65bf803eacbe16,
0x3f803f4e3e483f35,0xbf78bf713dc9bef1,0x3edb3f5cbf55bec4,0xbe16bf2c3f753f22,0xbf3ebf7d3f0e0000,0x3f043f67bf46be95,0x3eacbe793f7b3f6d,0xbf18bd49bf62bf7f,
0x3d493f18bf7bbf35,0x3e79beac3f7f3f62,0xbf67bf04bf0ebf6d,0x3f7d3f3e3e953f46,0x3f2c3e163f553f80,0xbf5cbedbbf22bf75,0x3f713f78be483ec4,0xbf4ebf803ef1bdc9,
0xbf5fbeb8bf22bf7b,0x3f7c3f273eac3f5c,0x3ea13f58bf62bec4,0x3cc9bf1d3f7d3f2c,0x3f7e3f313e953f55,0xbf7abf653d49bf18,0x3d97bf133f7f3f35,0xbecf3e89bf78bf67,
0xbefcbf6f3f463e48,0x3e2f3f42bf71bf04,0xbf73bf09bef1bf6d,0x3f803f4a3e163f3e,0x3dfb3f39bf75bf0e,0x3e60bee63f803f4e,0x3f7f3f513dc93f35,0xbf6abf773e79bedb,
0x3f553e483f353f80,0xbf7bbf0ebec4bf6d,0x3f0e3f7bbf350000,0xbe48bf553f6d3ec4,0xbf55be48bf35bf80,0x3f7b3f0e3ec43f6d,0xbf0ebf7b3f350000,0x3e483f55bf6dbec4,
0x3f0e3f7bbf358000,0xbe48bf553f6d3ec4,0xbf55be48bf35bf80,0x3f7b3f0e3ec43f6d,0xbf0ebf7b3f358000,0x3e483f55bf6dbec4,0x3f553e483f353f80,0xbf7bbf0ebec4bf6d,
0xbefc3eb8bf75bf55,0x3f513d973f3e3f7d,0x3f733f58bdc93f35,0xbf39bf7e3f04beac,0x3f4a3cc93f463f7b,0xbf7abee6bedbbf78,0xbf42bf7c3ef1bec4,0x3ecf3f77bf4ebd49,
0xbf5fbf6f3e95bf0e,0x3f133f7fbf2c3e16,0xbea13f09bf7fbf35,0x3f31bdfb3f5c3f71,0x3f1d3f80bf223e48,0xbe60bf653f673e79,0x3f27be2f3f623f6d,0xbf6abe89bf18bf80,
0x3edbbf043f7b3f35,0xbf4e3d49bf46bf75,0x3f2c3f7dbf0e3ec4,0xbe79bf713f623dc9,0x3eac3f78bf550000,0x3e16bf3e3f7f3ef1,0xbf80bf18be48bf6d,0x3f5c3f67be953f22,
0x3f673f5cbe483f35,0xbf18bf803f22be95,0xbf3e3e16bf55bf6d,0x3f783eac3ef13f7f,0xbf71be79bf0ebf80,0x3f7d3f2c3dc93f62,0x3d49bf4e3f7b3ec4,0xbf043edbbf75bf46,
0xbf313ea1bf62bf55,0x3f773e603f043f80,0x3f7c3f1d3dc93f6d,0xbf42bf6f3edbbf18,0xbecfbf7f3f46be48,0xbdfb3f51bf7dbeac,0xbf093efcbf75bf35,0x3f653cc93f2c3f78,
0xbf39bf733ef1bf0e,0x3e893f7abf5c3d49,0xbe2f3f4abf7fbec4,0x3f27beb83f673f4e,0x3f6a3d973f223f7b,0xbf7ebf13be16bf71,0xbf58bf5f3e95bf35,0x3ee63f80bf3e3e79,
0xbf7fbe95bec4bf80,0x3f623f46be483f55,0x3f22bef13f6d3f35,0xbf75bdc9bf0ebf7b,0x3dc93f75bf6d0000,0x3ef1bf223f7b3f0e,0xbf46bf623ec4bf35,0x3e953f7fbf553e48,
0xbdc9bf753f6d8000,0xbef13f22bf7bbf0e,0x3f463f62bec43f35,0xbe95bf7f3f55be48,0xbf7fbe95bec4bf80,0x3f623f46be483f55,0x3f22bef13f6d3f35,0xbf75bdc9bf0ebf7b,
0x3f7a3efc3dc93f7b,0xbf27bf6a3f04bf2c,0xbf31bf653ef1bf35,0x3dfb3f7cbf673e16,0x3f13bf1d3f753f0e,0xbf733cc9bf18bf71,0xbf6f3d97bf22bf6d,0x3f773f093d493f78,
0xbe603f5fbf7fbe48,0x3f42becf3f5c3f3e,0x3f39bee63f623f35,0xbf7ebe2fbedbbf7d,0x3f513f4abe953f55,0xbea1bf803f4ebeac,0xbeb8bf7f3f46bec4,0xbe893f58bf80be79,
0xbf18bf673f0ebf35,0xbd493f78bf753dc9,0x3f5c3f2cbe483f6d,0xbeacbf7d3f46bef1,0x3e16bf713f7b0000,0xbf3e3f04bf62bf22,0x3e793f80bf553ec4,0x3edbbf4e3f7f3e95,
0x3f4ebedb3f553f35,0xbf80be79be95bf7f,0xbf043f3ebf7bbec4,0x3f71be163f223f62,0x3f7d3eac3e483f80,0xbf2cbf5c3ef1bf46,0xbf783d49bf0ebf6d,0x3f673f18bdc93f75,
0xbee63f58bf7fbe48,0x3f6fbe893f2c3f4e,0x3f1dbf393f753ec4,0xbf7c3d97bf04bf67,0xbf423f13bf62bf0e,0x3f803dfb3eac3f78,0x3f5fbecf3f463f35,0xbf7abea1be16bf80,
0xbf65bf093dc9bf7b,0x3eb83f77bf3e3f18,0x3f4a3f31be953f6d,0xbe2fbf7f3f5cbedb,0xbf27bf513ef1bf55,0xbcc93f7ebf713e79,0x3efc3f6abf223f35,0x3e60bf733f7dbd49,
0x3f6d3ec400003f80,0xbec4bf6d3f35bf35,0xbf6dbec40000bf80,0x3ec43f6dbf353f35,0x3f6d3ec400003f80,0xbec4bf6d3f35bf35,0xbf6dbec40000bf80,0x3ec43f6dbf353f35,
0xbec43f6dbf808000,0x3f6dbec43f353f35,0x3ec4bf6d3f808000,0xbf6d3ec4bf35bf35,0xbec43f6dbf808000,0x3f6dbec43f353f35,0x3ec4bf6d3f808000,0xbf6d3ec4bf35bf35,
0xbd97bf7c3f62bf0e,0xbf313f4abf71be79,0x3e893f6fbf463f35,0x3f09bf653f7d3d49,0x3ea1bf7a3f7fbe48,0xbf6a3efcbf3ebf18,0xbdfb3f80bf753ec4,0x3f51bf273f5c3edb,
0x3f7fbe2f3ef13f55,0xbf39bf1d3eacbf78,0xbf773eb8bf22bf35,0x3f583ee6be163f80,0x3f733e603dc93f7b,0xbecfbf5f3f2cbf4e,0xbf7ebcc9be95bf6d,0x3f133f42bf043f67,
0xbf7d3eacbf0ebf35,0x3f3e3f04be953f7f,0x3f783d493e483f6d,0xbedbbf4e3f22bf62,0xbf183f67bf7b0000,0x3f80be793ef13f46,0x3f5cbf2c3f553ec4,0xbf71be16bdc9bf75,
0xbe16bf713f55bf35,0xbf2c3f5cbf75bdc9,0xbe793f80bf7b3ec4,0x3f67bf183f463ef1,0xbf4ebedb3e48bf80,0x3d493f78bf623f22,0x3f043f3ebf0e3f6d,0x3eacbf7d3f7fbe95,
0xbe2f3f7ebf753f0e,0x3f65bf313f4e3eac,0xbecfbf423f22bf6d,0xbefc3f7abf803e79,0x3f583e89bdc93f7b,0xbd97bf6f3f5cbf3e,0xbf803ea1bef1bf35,0x3f1d3f13bedb3f7d,
0xbf7c3dfbbe95bf55,0x3ee63f39bf183f71,0x3f6abf273f463ec4,0xbf5fbe603d49bf78,0xbf093f77bf7f3e48,0x3f7fbeb83f043f2c,0xbcc9bf733f62bf35,0xbf4a3f51bf67be16,
0xbf22bef13ec4bf80,0xbe953f7fbf7b3f0e,0xbdc93f75bf6d3f35,0x3f62bf463f553e48,0x3f46bf623f6d0000,0xbf753dc9be48bf55,0xbf7f3e95bec4bf35,0x3ef13f22bf0e3f7b,
0x3f46bf623f6d8000,0xbf753dc9be48bf55,0xbf7f3e95bec4bf35,0x3ef13f22bf0e3f7b,0x3f223ef1bec43f80,0x3e95bf7f3f7bbf0e,0x3dc9bf753f6dbf35,0xbf623f46bf55be48,
0xbf6f3f42bf46be48,0x3f4a3e2fbe163f71,0x3e60bf773f75bf35,0xbf733f39bf3ebe79,0x3cc9bf653f62bf55,0xbf5f3f58bf5cbd49,0x3f513dfbbdc93f6d,0x3d97bf6a3f67bf4e,
0xbeb8bf273f22bf7b,0xbf1d3f7cbf7d3eac,0x3f7abe893e953f35,0xbea1bf313f2cbf78,0x3f80bee63ef13f0e,0xbefcbf093f04bf80,0xbf133f7ebf7f3ec4,0x3f7fbecf3edb3f18,
0xbeac3f78bf7b3f35,0x3f7dbf2c3f223e95,0x3f80bf183f0e3ec4,0xbf04bedb3ef1bf7f,0x3f67bf5c3f550000,0xbf4ebd493dc9bf62,0xbf3ebe163e48bf6d,0xbe793f71bf753f46,
0xbf713e79be48bf35,0x3e163f3ebf463f75,0x3d493f4ebf553f6d,0x3f5cbf673f62bdc9,0x3edb3f04bf0e3f80,0x3f18bf803f7fbef1,0x3f2cbf7d3f7bbec4,0xbf783eacbe95bf22,
0x3dfb3f31bf463f7b,0x3f58bf733f67be79,0xbf7f3f13bef1bec4,0x3eb83efcbf183f80,0x3e89bf6a3f75bf55,0xbf7c3f42bf2cbe16,0x3f65be603dc93f35,0x3cc9bf4a3f5cbf71,
0xbf7e3f39bf22be48,0x3f093ea1bedb3f78,0x3d97bf513f62bf6d,0xbf6f3f5fbf4e3d49,0x3f77becf3e953f0e,0xbe2fbf273f3ebf7d,0xbee63f7abf7f3f35,0x3f80bf1d3f043eac,
0x3e483f0ebf353f80,0x3f55bf7b3f6dbec4,0x3f7bbf553f350000,0xbf0ebe483ec4bf6d,0xbe48bf0e3f35bf80,0xbf553f7bbf6d3ec4,0xbf7b3f55bf350000,0x3f0e3e48bec43f6d,
0xbf7b3f55bf358000,0x3f0e3e48bec43f6d,0x3e483f0ebf353f80,0x3f55bf7b3f6dbec4,0x3f7bbf553f358000,0xbf0ebe483ec4bf6d,0xbe48bf0e3f35bf80,0xbf553f7bbf6d3ec4,
0x3f1d3cc9be953f55,0x3f09bf733f80bf4e,0xbf273f7cbf7f3f35,0x3f6fbefc3e793edb,0xbe89becf3f22bf7b,0xbf513f7fbf713f04,0x3f65bf7a3f62bec4,0xbf393dfb3e16bf3e,
0xbf4a3f80bf753f0e,0x3f58bea13d493f18,0xbf423e2f3dc9bf35,0xbeb83f5fbf783f67,0x3f77bf6a3f46be48,0xbf13bd973eacbf5c,0x3ee63e60bef13f6d,0x3f31bf7e3f7dbf2c,
0x3f2cbe16be483f35,0x3f04bf673f7fbf62,0x3f71bf783f55bec4,0xbf183d493e95bf46,0xbf803f4ebf0e0000,0x3e793eacbf223f75,0xbedb3f5cbf7b3f6d,0x3f7dbf3e3ef13dc9,
0xbf3e3f7dbf7b3f35,0x3f5cbedb3dc93ef1,0x3eac3e79bf0e3f6d,0x3f4ebf803f75bf22,0x3d49bf183f55bf80,0xbf783f71bf463e95,0xbf673f04be48bec4,0xbe163f2cbf623f7f,
0x3ecf3d97bef13f55,0x3f4abf7c3f78bf3e,0xbf093f5fbf7f3f6d,0x3f73bf313eac3e16,0xbf803f65bf223e48,0x3e893e60bf183f67,0xbf133dfb3e95bf35,0xbf273f6fbf803f5c,
0xbf6a3f7fbf623f0e,0x3f1dbe2fbe793f2c,0xbf583efcbdc9bec4,0xbea13f39bf713f7d,0xbcc9bee63f46bf7b,0xbf773f7abf4e3edb,0x3f51bf7e3f75bf35,0xbf423eb83d49bf04,
0x3e95bf223f6dbf80,0xbf7f3f62bf0e3e48,0xbef13dc93ec4bf35,0xbf463f75bf7b3f55,0xbf753f46bec40000,0xbdc93ef1bf553f7b,0xbf623f7fbf6d3f35,0x3f22be95be483f0e,
0x3f75bf463ec48000,0x3dc9bef13f55bf7b,0x3f62bf7f3f6dbf35,0xbf223e953e48bf0e,0x3e95bf223f6dbf80,0xbf7f3f62bf0e3e48,0xbef13dc93ec4bf35,0xbf463f75bf7b3f55,
0x3f13bf4a3f7fbf7b,0xbf653f39be79bd49,0x3f6fbf7f3f62bf35,0xbefc3e603eacbf18,0xbf093e893e95bf0e,0xbf423f6abf7d3f67,0x3cc9bea13f46bf6d,0xbf7e3f7cbf3e3f04,
0x3f51bf1d3dc93e48,0x3ee6bf313f78bf80,0x3eb8bd97bef13f35,0x3f5fbf7a3f71bf4e,0x3f58bf773f75bf55,0xbf273ecf3e16bedb,0x3f80bf733f22bec4,0xbdfbbe2f3f2cbf5c,
0x3f78bf803f55bf35,0xbeac3e163ef1bf22,0x3f4ebf673f7bbf6d,0xbf2c3f043dc9be95,0x3f5cbf3e3e480000,0x3edbbf183f75bf7f,0x3f7dbf713f0ebec4,0x3d49be793f46bf62,
0x3e79bd49bf0e3f35,0x3f71bf7d3f62bf46,0x3f18bedbbe483ec4,0x3f3ebf5c3f7fbf75,0xbf043f2cbf7b3f80,0x3f67bf4e3e95bdc9,0xbe163eacbf553f6d,0x3f80bf783f22bef1,
0x3f27bf13bdc93e48,0x3f39bf4a3f80bf7d,0x3efcbecfbe953ec4,0x3f58bf653f78bf71,0x3ea1be60bef13f0e,0x3f6fbf773f67bf5c,0x3dfbbcc9bf223f35,0x3f7cbf7f3f4ebf3e,
0xbf423f51bf7f3f7b,0x3f31bf1dbd493e16,0xbf5f3f6abf753f6d,0x3f09bee6be793eac,0xbf733f7abf623f55,0x3eb8be89bedb3f04,0xbf7e3f80bf463f35,0x3e2fbd97bf183f2c,
0x3f35bf35bf803f80,0xbf353f3500000000,0x3f35bf35bf803f80,0xbf353f3500000000,0x3f35bf35bf803f80,0xbf353f3500000000,0x3f35bf35bf803f80,0xbf353f3500000000,
0x3f35bf3580008000,0x3f35bf35bf803f80,0x3f35bf3580008000,0x3f35bf35bf803f80,0x3f35bf3580008000,0x3f35bf35bf803f80,0x3f35bf3580008000,0x3f35bf35bf803f80,
0x3f733f7abe95be48,0xbf6fbf773eac3e79,0x3f7e3f80bdc90000,0xbf7cbf7f3e163d49,0x3f423f51bf22bf0e,0xbf39bf4a3f2c3f18,0x3f5f3f6abef1bec4,0xbf58bf653f043edb,
0xbea1be60bf75bf7b,0x3eb83e893f713f78,0xbdfbbcc9bf7fbf80,0x3e2f3d973f7d3f80,0xbf27bf13bf46bf55,0x3f313f1d3f3e3f4e,0xbefcbecfbf62bf6d,0x3f093ee63f5c3f67,
0xbf5cbf3ebf0ebf35,0x3f673f4e3ef13f22,0xbf7dbf71be48bec4,0x3f803f783dc93e95,0xbe79bd49bf7bbf80,0x3eac3e163f753f7f,0xbf18bedbbf55bf6d,0x3f2c3f043f463f62,
0xbf04bf2c3f553f35,0x3edb3f18bf62bf46,0xbe16beac3f7b3f6d,0x3d493e79bf7fbf75,0xbf78bf803e488000,0x3f713f7dbe95bdc9,0xbf4ebf673f0e3ec4,0x3f3e3f5cbf22bef1,
0x3f093e893f623f7b,0xbf27becfbf4ebf71,0xbcc9bea13f7f3f6d,0xbdfb3e2fbf80bf78,0xbf13bf4a3f463f0e,0x3ee63f31bf5cbf2c,0xbf6fbf7f3e950000,0x3f5f3f7abedbbe16,
0x3f583f77bef1be48,0xbf42bf6a3f183eac,0x3f803f733dc93ec4,0xbf7ebf7c3d49be79,0x3f513f1d3f223f55,0xbf65bf39bf04bf3e,0x3eb83d973f753f80,0xbefcbe60bf67bf7d,
0x3ef13dc93f6d3f80,0xbf22be95bf55bf7b,0x3f753f463ec43f35,0xbf7fbf62be48bf0e,0x3f623f7fbec40000,0xbf46bf753f0e3e48,0x3e953f22bf6dbf35,0xbdc9bef13f7b3f55,
0x3f623f7fbec48000,0xbf46bf753f0e3e48,0x3e953f22bf6dbf35,0xbdc9bef13f7b3f55,0xbef1bdc9bf6dbf80,0x3f223e953f553f7b,0xbf75bf46bec4bf35,0x3f7f3f623e483f0e,
0xbcc93ee6bf7fbf55,0x3e89be603f7d3f71,0x3f513f7ebef10000,0xbf27bf6f3f2c3e79,0xbf6abf7f3e95be48,0x3f4a3f7cbf04bd49,0xbf58befcbf22bf6d,0x3f733f313edb3f4e,
0xbf80bf65bdc9bf0e,0x3f773f7abe163eac,0xbf13bdfbbf62bf80,0x3f423eb83f3e3f78,0x3ecfbd973f753f7b,0xbf1dbe2fbf5cbf80,0xbf09bf5f3f463ec4,0x3ea13f39bf67bf18,
0xbd49bf183f7b3f35,0xbe793eacbf7fbf62,0x3f673f043f0e3f6d,0xbf7dbf3ebe95bf46,0xbf2cbe16bf55bf80,0x3f5c3edb3f223f75,0xbf71bf783e48bec4,0x3f4e3f80bef13dc9,
0x3f803f4e3e483f35,0xbf78bf713dc9bef1,0x3edb3f5cbf55bec4,0xbe16bf2c3f753f22,0xbf3ebf7d3f0e8000,0x3f043f67bf46be95,0x3eacbe793f7b3f6d,0xbf18bd49bf62bf7f,
0xbe893ecfbf7fbf55,0x3f13bd973f673f78,0x3f653f7abe953ec4,0xbf31bf7e3f18bd49,0x3f1dbcc93f623f7b,0xbf58bea1bf2cbf7d,0xbf27bf7c3f220000,0x3eb83f5fbf5cbeac,
0xbf77bf6a3dc9bf0e,0x3f513f7fbedb3e79,0xbee63e60bf75bf6d,0x3f393dfb3f4e3f80,0x3f4a3f80bef13e48,0xbf09bf733f3e3e16,0x3f423e2f3f463f80,0xbf6fbefcbf04bf71,
0x3f553e483f353f80,0xbf7bbf0ebec4bf6d,0x3f0e3f7bbf350000,0xbe48bf553f6d3ec4,0xbf55be48bf35bf80,0x3f7b3f0e3ec43f6d,0xbf0ebf7b3f350000,0x3e483f55bf6dbec4,
0x3f0e3f7bbf358000,0xbe48bf553f6d3ec4,0xbf55be48bf35bf80,0x3f7b3f0e3ec43f6d,0xbf0ebf7b3f358000,0x3e483f55bf6dbec4,0x3f553e483f353f80,0xbf7bbf0ebec4bf6d,
0xbf77becfbef1bf7b,0x3f7c3f423d493f4e,0x3ee63f7abf460000,0xbcc9bf4a3f783edb,0x3f7e3f393dc93f55,0xbf58bf733eacbf04,0xbd97bf513f753ec4,0xbeb83efcbf7dbf3e,
0xbe89bf6a3f623e48,0xbe2f3f27bf80bf18,0xbf65be60bf22bf80,0x3f803f1d3e793f67,0xbdfb3f31bf7fbf0e,0x3f09bea13f713f5c,0x3f7f3f133e953f6d,0xbf6fbf5f3e16bf2c,
0x3f673f5cbe483f35,0xbf18bf803f22be95,0xbf3e3e16bf55bf6d,0x3f783eac3ef13f7f,0xbf71be79bf0ebf80,0x3f7d3f2c3dc93f62,0x3d49bf4e3f7b3ec4,0xbf043edbbf75bf46,
0xbedb3f04bf7bbf35,0x3f4ebd493f463f75,0xbf2cbf7d3f0ebec4,0x3e793f71bf62bdc9,0xbeacbf783f558000,0xbe163f3ebf7fbef1,0x3f803f183e483f6d,0xbf5cbf673e95bf22,
0xbcc9bf653f753e48,0xbefc3f09bf78bf2c,0xbf513dfbbf46bf6d,0x3f7f3ecf3eac3f7d,0x3f6f3f42bdc93f55,0xbf1dbf7c3f18bedb,0xbe60bf773f620000,0xbea13f31bf80bf04,
0x3f803ee63e953f7b,0xbf5fbf583e79bf3e,0xbf13bf7e3f22bec4,0x3d973f6abf71be16,0xbeb83f27bf7fbf0e,0x3f4abe2f3f4e3f67,0x3f7a3e893ef13f80,0xbf73bf393d49bf5c,
0x3f7f3e953ec43f80,0xbf62bf463e48bf55,0xbf223ef1bf6dbf35,0x3f753dc93f0e3f7b,0xbdc9bf753f6d0000,0xbef13f22bf7bbf0e,0x3f463f62bec43f35,0xbe95bf7f3f55be48,
0x3dc93f75bf6d8000,0x3ef1bf223f7b3f0e,0xbf46bf623ec4bf35,0x3e953f7fbf553e48,0x3f7f3e953ec43f80,0xbf62bf463e48bf55,0xbf223ef1bf6dbf35,0x3f753dc93f0e3f7b,
0xbf09bf773f22bf0e,0xbd973f6fbf78bd49,0xbcc93f73bf750000,0x3f1dbf133f713f18,0xbf7cbdfbbef1bf7b,0x3f653f31be163f67,0x3f6a3f27bdc93f6d,0xbefcbf7a3f2cbf04,
0x3f58be893f463f55,0xbf7fbeb8be79bf80,0xbf80bea1be95bf80,0x3f4a3f51beac3f4e,0xbe2fbf7e3f62be48,0xbee63f39bf7dbedb,0xbecf3f42bf7fbec4,0x3f5fbe603f3e3f5c,
0xbf4e3edbbf55bf35,0x3f803e793e953f7f,0x3f04bf3e3f7b3ec4,0xbf713e16bf22bf62,0xbf7dbeacbe48bf80,0x3f2c3f5cbef13f46,0x3f78bd493f0e3f6d,0xbf67bf183dc9bf75,
0xbf18bf673f0ebf35,0xbd493f78bf753dc9,0x3f5c3f2cbe483f6d,0xbeacbf7d3f46bef1,0x3e16bf713f7b8000,0xbf3e3f04bf62bf22,0x3e793f80bf553ec4,0x3edbbf4e3f7f3e95,
0x3ea13f7abf463f0e,0x3ecfbf5f3f803e16,0xbdfbbf803f62bec4,0xbf133f42bf78beac,0xbd973f7cbf753e48,0x3f39bf1d3f673f04,0x3e89bf6f3f7f0000,0xbf583ee6bf4ebf2c,
0xbf733e60bf22bf55,0x3f6a3efcbd493f7d,0x3f7ebcc93ef13f6d,0xbf51bf273e79bf71,0xbf7fbe2fbe95bf7b,0x3f313f4abedb3f5c,0x3f773eb83dc93f80,0xbf09bf653f18bf3e,
0x3f6d3ec400003f80,0xbec4bf6d3f35bf35,0xbf6dbec40000bf80,0x3ec43f6dbf353f35,0x3f6d3ec400003f80,0xbec4bf6d3f35bf35,0xbf6dbec40000bf80,0x3ec43f6dbf353f35,
0xbec43f6dbf808000,0x3f6dbec43f353f35,0x3ec4bf6d3f808000,0xbf6d3ec4bf35bf35,0xbec43f6dbf808000,0x3f6dbec43f353f35,0x3ec4bf6d3f808000,0xbf6d3ec4bf35bf35,
0x3f27bf513f753e48,0xbf803dfbbedbbf5c,0xbefc3f6abf7f0000,0x3f7abea13f183f3e,0x3f65bf093f463f0e,0xbf6fbe89bd49bf7d,0xbf4a3f31bf62bec4,0x3f7c3d973e793f71,
0x3f423f13be953f7b,0xbcc9bf7e3f67bf04,0xbf5fbecf3dc9bf80,0x3e603f73bf4e3f2c,0x3ee63f58bf223f55,0x3eb8bf773f80be16,0xbf1dbf393ef1bf6d,0xbe2f3f7fbf783eac,
0xbe16bf713f55bf35,0xbf2c3f5cbf75bdc9,0xbe793f80bf7b3ec4,0x3f67bf183f463ef1,0xbf4ebedb3e48bf80,0x3d493f78bf623f22,0x3f043f3ebf0e3f6d,0x3eacbf7d3f7fbe95,
0x3f7dbeac3f0e3f35,0xbf3ebf043e95bf7f,0xbf78bd49be48bf6d,0x3edb3f4ebf223f62,0x3f18bf673f7b8000,0xbf803e79bef1bf46,0xbf5c3f2cbf55bec4,0x3f713e163dc93f75,
0xbf13bf1d3ef1bf7b,0xbea13f80bf7d3edb,0x3f6f3d973dc93f6d,0xbe89bf583f3ebf5c,0xbf7a3efcbf22bf0e,0x3f423ecfbe793f80,0x3f31bf653f750000,0xbf7e3e2fbeacbf4e,
0x3f51bf4a3f623e48,0xbf73bcc9be16bf67,0xbeb83f7fbf7f3ec4,0x3f77bf093f2c3f04,0xbe60bf5f3f46bf55,0xbf273f6abf783d49,0x3f393ee6be953f80,0x3dfbbf7c3f71bf18,
0x3f223ef1bec43f80,0x3e95bf7f3f7bbf0e,0x3dc9bf753f6dbf35,0xbf623f46bf55be48,0xbf463f62bf6d0000,0x3f75bdc93e483f55,0x3f7fbe953ec43f35,0xbef1bf223f0ebf7b,
0xbf463f62bf6d8000,0x3f75bdc93e483f55,0x3f7fbe953ec43f35,0xbef1bf223f0ebf7b,0xbf22bef13ec4bf80,0xbe953f7fbf7b3f0e,0xbdc93f75bf6d3f35,0x3f62bf463f553e48,
0x3f6abd973dc93f55,0xbdfbbf513f4ebf67,0xbf583f5fbf620000,0x3f65bcc93d493f5c,0xbf393f73bf753e48,0x3f77be603e793f3e,0xbe2fbf4a3f46bf6d,0xbf423f6fbf713e16,
0xbecf3f7fbf7f3f0e,0x3f7ebf133f183edb,0xbf09befc3ef1bf80,0xbee63f80bf803f04,0xbf31bea13e95bf7b,0xbe893f7abf783f2c,0x3f7cbf1d3f223ec4,0xbf27beb83eacbf7d,
0x3f71be793e483f35,0xbe16bf3e3f46bf75,0xbd49bf4e3f55bf6d,0xbf5c3f67bf623dc9,0xbedbbf043f0ebf80,0xbf183f80bf7f3ef1,0xbf2c3f7dbf7b3ec4,0x3f78beac3e953f22,
0xbeac3f78bf7b3f35,0x3f7dbf2c3f223e95,0x3f80bf183f0e3ec4,0xbf04bedb3ef1bf7f,0x3f67bf5c3f558000,0xbf4ebd493dc9bf62,0xbf3ebe163e48bf6d,0xbe793f71bf753f46,
0x3f4abcc9bdc93f55,0x3e60bf653f71bf5c,0xbf423f7cbf753ec4,0x3f6abe893e163f2c,0xbefcbeb83ef1bf7b,0xbf133f7fbf803f18,0x3f73bf583f460000,0xbf31bdfb3e79bf67,
0xbf1d3f80bf7f3f0e,0x3f7abee63eac3f04,0xbf27be2f3e95bf6d,0xbecf3f77bf7d3f3e,0x3f5fbf6f3f62be48,0xbf513d973d49bf4e,0x3ea13f09bf223f80,0x3f39bf7e3f78bedb,
0x3e483f0ebf353f80,0x3f55bf7b3f6dbec4,0x3f7bbf553f350000,0xbf0ebe483ec4bf6d,0xbe48bf0e3f35bf80,0xbf553f7bbf6d3ec4,0xbf7b3f55bf350000,0x3f0e3e48bec43f6d,
0xbf7b3f55bf358000,0x3f0e3e48bec43f6d,0x3e483f0ebf353f80,0x3f55bf7b3f6dbec4,0x3f7bbf553f358000,0xbf0ebe483ec4bf6d,0xbe48bf0e3f35bf80,0xbf553f7bbf6d3ec4,
0xbdfb3f39bf623f7b,0x3f7abf653f3ebe16,0xbf7f3f51bf220000,0x3ecf3e89bf043f71,0x3efcbf6f3f7fbf55,0xbf7c3f27bedbbe79,0x3f73bf093e953ec4,0xbcc9bf1d3f4ebf80,
0xbf7e3f31bef1be48,0x3e603ee6bf2c3f7d,0xbd97bf133f46bf80,0xbf6a3f77bf5c3eac,0x3f5fbeb83dc93f0e,0x3e2fbf423f67bf78,0xbea13f58bf753f6d,0x3f80bf4a3f183d49,
0xbf3e3f7dbf7b3f35,0x3f5cbedb3dc93ef1,0x3eac3e79bf0e3f6d,0x3f4ebf803f75bf22,0x3d49bf183f55bf80,0xbf783f71bf463e95,0xbf673f04be48bec4,0xbe163f2cbf623f7f,
0xbf2c3e163e48bf35,0xbf043f67bf7f3f62,0xbf713f78bf553ec4,0x3f18bd49be953f46,0x3f80bf4e3f0e8000,0xbe79beac3f22bf75,0x3edbbf5c3f7bbf6d,0xbf7d3f3ebef1bdc9,
0xbf6f3f27be95be48,0xbdfb3f13bf5c3f80,0xbe60be893f22bf6d,0xbf653f80bf673f18,0x3f31bf733f7fbf55,0xbf5f3f09be16beac,0x3f7cbf4a3ef10000,0xbd97becf3f3ebf78,
0x3eb8bf423f75bf7b,0xbf7e3f51bf043d49,0x3f7abf773f46bec4,0xbee6bcc93edbbf4e,0x3f39bea1bdc93f0e,0x3efcbf583f7dbf71,0xbe2f3f1dbf623f80,0x3f7fbf6a3f2cbe79,
0xbe953f22bf6d3f80,0x3f7fbf623f0ebe48,0x3ef1bdc9bec43f35,0x3f46bf753f7bbf55,0x3f75bf463ec40000,0x3dc9bef13f55bf7b,0x3f62bf7f3f6dbf35,0xbf223e953e48bf0e,
0xbf753f46bec48000,0xbdc93ef1bf553f7b,0xbf623f7fbf6d3f35,0x3f22be95be483f0e,0xbe953f22bf6d3f80,0x3f7fbf623f0ebe48,0x3ef1bdc9bec43f35,0x3f46bf753f7bbf55,
0xbf7c3f7ebf463f0e,0x3ea1bcc9bf043f3e,0xbf6a3f42be950000,0xbe893f09bf673f7d,0xbe603efcbf623f7b,0x3f7fbf6f3f18beac,0xbf393f65bf7f3f6d,0x3f4abf133d493e79,
0xbe2fbdfb3f22bf55,0xbf733f80bf5c3f2c,0x3ecfbf273f75bf80,0xbf773f58bedb3e16,0xbf7a3f5fbef13e48,0xbd973eb8bf4e3f71,0xbf313ee63dc9bec4,0xbf1d3f51bf803f78,
0xbe793d493f0ebf35,0xbf713f7dbf623f46,0xbf183edb3e48bec4,0xbf3e3f5cbf7f3f75,0x3f04bf2c3f7bbf80,0xbf673f4ebe953dc9,0x3e16beac3f55bf6d,0xbf803f78bf223ef1,
0x3f78bf803f55bf35,0xbeac3e163ef1bf22,0x3f4ebf673f7bbf6d,0xbf2c3f043dc9be95,0x3f5cbf3e3e488000,0x3edbbf183f75bf7f,0x3f7dbf713f0ebec4,0x3d49be793f46bf62,
0x3f7fbf7c3f22bf0e,0x3cc9bdfb3f3ebf4e,0x3f77bf6f3ef1bec4,0x3e60bea13f5cbf67,0x3f65bf583e95be48,0x3ecfbefc3f71bf78,0x3f4abf393dc90000,0x3f13bf273f7dbf80,
0xbd973e2fbf463f55,0x3f80bf7e3f2cbf18,0xbe893eb8bf623f6d,0x3f7abf733f04bedb,0xbee63f09bf753f7b,0x3f6abf5f3eacbe79,0xbf1d3f31bf7f3f80,0x3f51bf423e16bd49,
0x3f35bf35bf803f80,0xbf353f3500000000,0x3f35bf35bf803f80,0xbf353f3500000000,0x3f35bf35bf803f80,0xbf353f3500000000,0x3f35bf35bf803f80,0xbf353f3500000000,
0x3f35bf3580008000,0x3f35bf35bf803f80,0x3f35bf3580008000,0x3f35bf35bf803f80,0x3f35bf3580008000,0x3f35bf35bf803f80,0x3f35bf3580008000,0x3f35bf35bf803f80,
0x3ee63f09bf62bf55,0xbecfbefc3f673f5c,0x3f1d3f31bf46bf35,0xbf13bf273f4e3f3e,0x3d973e2fbf7fbf7b,0xbcc9bdfb3f803f7d,0x3e893eb8bf75bf6d,0xbe60bea13f783f71,
0xbf65bf58bef1bf0e,0x3f6a3f5f3edb3f04,0xbf4abf39bf22bf35,0x3f513f423f183f2c,0xbf7fbf7cbdc9be48,0x3f803f7e3d493e16,0xbf77bf6fbe95bec4,0x3f7a3f733e793eac,
0xbf04bf2c3f553f35,0x3edb3f18bf62bf46,0xbe16beac3f7b3f6d,0x3d493e79bf7fbf75,0xbf78bf803e480000,0x3f713f7dbe95bdc9,0xbf4ebf673f0e3ec4,0x3f3e3f5cbf22bef1,
0x3f5c3f3e3f0e3f35,0xbf67bf4ebef1bf22,0x3f7d3f713e483ec4,0xbf80bf78bdc9be95,0x3e793d493f7b3f80,0xbeacbe16bf75bf7f,0x3f183edb3f553f6d,0xbf2cbf04bf46bf62,
0x3e603efcbf75bf55,0xbd97beb83f7d3f67,0x3f393f65bf22bec4,0xbf1dbf513f3e3f04,0x3f7c3f7ebdc93e48,0xbf73bf803e79bd49,0x3f6a3f423ef13f35,0xbf77bf58beacbf18,
0xbf7abf5fbe95bf0e,0x3f7f3f6f3e163edb,0xbf31bee6bf46bf6d,0x3f4a3f133f2c3f5c,0xbe2f3dfbbf7fbf7b,0x3ea13cc93f783f80,0x3ecf3f27bf62bf35,0xbe89bf093f713f4e,
0xbef1bdc9bf6dbf80,0x3f223e953f553f7b,0xbf75bf46bec4bf35,0x3f7f3f623e483f0e,0xbf62bf7f3ec40000,0x3f463f75bf0ebe48,0xbe95bf223f6d3f35,0x3dc93ef1bf7bbf55,
0xbf62bf7f3ec48000,0x3f463f75bf0ebe48,0xbe95bf223f6d3f35,0x3dc93ef1bf7bbf55,0x3ef13dc93f6d3f80,0xbf22be95bf55bf7b,0x3f753f463ec43f35,0xbf7fbf62be48bf0e,
0x3f393ea13f463f7b,0xbf5fbf09bf18bf67,0xbe2fbf1d3f753f35,0xbd973ecfbf80bf5c,0x3eb83f42bf62bf0e,0xbdfbbf133f783f3e,0x3f7a3f77bdc93ec4,0xbf65bf803eacbe16,
0x3f313f73bf22be48,0xbefcbf583f4e3edb,0x3f7c3f4a3e953f35,0xbf7fbf6abd49bf04,0xbf6fbf27bef1bf55,0x3f7e3f513e793f2c,0xbe603e89bf7fbf6d,0x3ee6bcc93f713f7d,
0xbf80bf4ebe48bf35,0x3f783f71bdc93ef1,0xbedbbf5c3f553ec4,0x3e163f2cbf75bf22,0x3f3e3f7dbf0e0000,0xbf04bf673f463e95,0xbeac3e79bf7bbf6d,0x3f183d493f623f7f,
0xbd49bf183f7b3f35,0xbe793eacbf7fbf62,0x3f673f043f0e3f6d,0xbf7dbf3ebe95bf46,0xbf2cbe16bf55bf80,0x3f5c3edb3f223f75,0xbf71bf783e48bec4,0x3f4e3f80bef13dc9,
0x3efc3f6fbf46be48,0xbe2fbf423f713f04,0x3f733f093ef13f6d,0xbf80bf4abe16bf3e,0xbdfbbf393f753f0e,0xbe603ee6bf80bf4e,0xbf7fbf51bdc9bf35,0x3f6a3f77be793edb,
0xbf5fbeb8bf22bf7b,0x3f7c3f273eac3f5c,0x3ea13f58bf62bec4,0x3cc9bf1d3f7d3f2c,0x3f7e3f313e953f55,0xbf7abf653d49bf18,0x3d97bf133f7f3f35,0xbecf3e89bf78bf67,
0x3f553e483f353f80,0xbf7bbf0ebec4bf6d,0x3f0e3f7bbf350000,0xbe48bf553f6d3ec4,0xbf55be48bf35bf80,0x3f7b3f0e3ec43f6d,0xbf0ebf7b3f350000,0x3e483f55bf6dbec4,
0x3f0e3f7bbf358000,0xbe48bf553f6d3ec4,0xbf55be48bf35bf80,0x3f7b3f0e3ec43f6d,0xbf0ebf7b3f358000,0x3e483f55bf6dbec4,0x3f553e483f353f80,0xbf7bbf0ebec4bf6d,
0xbf5fbf6f3e95bf0e,0x3f133f7fbf2c3e16,0xbea13f09bf7fbf35,0x3f31bdfb3f5c3f71,0x3f1d3f80bf223e48,0xbe60bf653f673e79,0x3f27be2f3f623f6d,0xbf6abe89bf18bf80,
0x3efcbeb83f753f55,0xbf51bd97bf3ebf7d,0xbf73bf583dc9bf35,0x3f393f7ebf043eac,0xbf4abcc9bf46bf7b,0x3f7a3ee63edb3f78,0x3f423f7cbef13ec4,0xbecfbf773f4e3d49,
0xbedb3f04bf7bbf35,0x3f4ebd493f463f75,0xbf2cbf7d3f0ebec4,0x3e793f71bf62bdc9,0xbeacbf783f550000,0xbe163f3ebf7fbef1,0x3f803f183e483f6d,0xbf5cbf673e95bf22,
0xbf67bf5c3e48bf35,0x3f183f80bf223e95,0x3f3ebe163f553f6d,0xbf78beacbef1bf7f,0x3f713e793f0e3f80,0xbf7dbf2cbdc9bf62,0xbd493f4ebf7bbec4,0x3f04bedb3f753f46,
0x3f393f73bef13f0e,0xbe89bf7a3f5cbd49,0x3e2fbf4a3f7f3ec4,0xbf273eb8bf67bf4e,0xbf6abd97bf22bf7b,0x3f7e3f133e163f71,0x3f583f5fbe953f35,0xbee6bf803f3ebe79,
0xbf313ea1bf62bf55,0x3f773e603f043f80,0x3f7c3f1d3dc93f6d,0xbf42bf6f3edbbf18,0xbecfbf7f3f46be48,0xbdfb3f51bf7dbeac,0xbf093efcbf75bf35,0x3f653cc93f2c3f78,
0xbf7fbe95bec4bf80,0x3f623f46be483f55,0x3f22bef13f6d3f35,0xbf75bdc9bf0ebf7b,0x3dc93f75bf6d0000,0x3ef1bf223f7b3f0e,0xbf46bf623ec4bf35,0x3e953f7fbf553e48,
0xbdc9bf753f6d8000,0xbef13f22bf7bbf0e,0x3f463f62bec43f35,0xbe95bf7f3f55be48,0xbf7fbe95bec4bf80,0x3f623f46be483f55,0x3f22bef13f6d3f35,0xbf75bdc9bf0ebf7b,
0xbe603f5fbf7fbe48,0x3f42becf3f5c3f3e,0x3f39bee63f623f35,0xbf7ebe2fbedbbf7d,0x3f513f4abe953f55,0xbea1bf803f4ebeac,0xbeb8bf7f3f46bec4,0xbe893f58bf80be79,
0xbf7abefcbdc9bf7b,0x3f273f6abf043f2c,0x3f313f65bef13f35,0xbdfbbf7c3f67be16,0xbf133f1dbf75bf0e,0x3f73bcc93f183f71,0x3f6fbd973f223f6d,0xbf77bf09bd49bf78,
0x3f183f67bf0e3f35,0x3d49bf783f75bdc9,0xbf5cbf2c3e48bf6d,0x3eac3f7dbf463ef1,0xbe163f71bf7b0000,0x3f3ebf043f623f22,0xbe79bf803f55bec4,0xbedb3f4ebf7fbe95,
0xbf4e3edbbf55bf35,0x3f803e793e953f7f,0x3f04bf3e3f7b3ec4,0xbf713e16bf22bf62,0xbf7dbeacbe48bf80,0x3f2c3f5cbef13f46,0x3f78bd493f0e3f6d,0xbf67bf183dc9bf75,
0x3f653f09bdc93f7b,0xbeb8bf773f3ebf18,0xbf4abf313e95bf6d,0x3e2f3f7fbf5c3edb,0x3f273f51bef13f55,0x3cc9bf7e3f71be79,0xbefcbf6a3f22bf35,0xbe603f73bf7d3d49,
0xbee63f58bf7fbe48,0x3f6fbe893f2c3f4e,0x3f1dbf393f753ec4,0xbf7c3d97bf04bf67,0xbf423f13bf62bf0e,0x3f803dfb3eac3f78,0x3f5fbecf3f463f35,0xbf7abea1be16bf80,
0x3f6d3ec400003f80,0xbec4bf6d3f35bf35,0xbf6dbec40000bf80,0x3ec43f6dbf353f35,0x3f6d3ec400003f80,0xbec4bf6d3f35bf35,0xbf6dbec40000bf80,0x3ec43f6dbf353f35,
0xbec43f6dbf808000,0x3f6dbec43f353f35,0x3ec4bf6d3f808000,0xbf6d3ec4bf35bf35,0xbec43f6dbf808000,0x3f6dbec43f353f35,0x3ec4bf6d3f808000,0xbf6d3ec4bf35bf35,
0x3f7fbe2f3ef13f55,0xbf39bf1d3eacbf78,0xbf773eb8bf22bf35,0x3f583ee6be163f80,0x3f733e603dc93f7b,0xbecfbf5f3f2cbf4e,0xbf7ebcc9be95bf6d,0x3f133f42bf043f67,
0x3d973f7cbf623f0e,0x3f31bf4a3f713e79,0xbe89bf6f3f46bf35,0xbf093f65bf7dbd49,0xbea13f7abf7f3e48,0x3f6abefc3f3e3f18,0x3dfbbf803f75bec4,0xbf513f27bf5cbedb,
0x3f7dbeac3f0e3f35,0xbf3ebf043e95bf7f,0xbf78bd49be48bf6d,0x3edb3f4ebf223f62,0x3f18bf673f7b0000,0xbf803e79bef1bf46,0xbf5c3f2cbf55bec4,0x3f713e163dc93f75,
0x3e163f71bf553f35,0x3f2cbf5c3f753dc9,0x3e79bf803f7bbec4,0xbf673f18bf46bef1,0x3f4e3edbbe483f80,0xbd49bf783f62bf22,0xbf04bf3e3f0ebf6d,0xbeac3f7dbf7f3e95,
0x3f7cbdfb3e953f55,0xbee6bf393f18bf71,0xbf6a3f27bf46bec4,0x3f5f3e60bd493f78,0x3f09bf773f7fbe48,0xbf7f3eb8bf04bf2c,0x3cc93f73bf623f35,0x3f4abf513f673e16,
0xbe2f3f7ebf753f0e,0x3f65bf313f4e3eac,0xbecfbf423f22bf6d,0xbefc3f7abf803e79,0x3f583e89bdc93f7b,0xbd97bf6f3f5cbf3e,0xbf803ea1bef1bf35,0x3f1d3f13bedb3f7d,
0xbf22bef13ec4bf80,0xbe953f7fbf7b3f0e,0xbdc93f75bf6d3f35,0x3f62bf463f553e48,0x3f46bf623f6d0000,0xbf753dc9be48bf55,0xbf7f3e95bec4bf35,0x3ef13f22bf0e3f7b,
0x3f46bf623f6d8000,0xbf753dc9be48bf55,0xbf7f3e95bec4bf35,0x3ef13f22bf0e3f7b,0x3f223ef1bec43f80,0x3e95bf7f3f7bbf0e,0x3dc9bf753f6dbf35,0xbf623f46bf55be48,
0xbeb8bf273f22bf7b,0xbf1d3f7cbf7d3eac,0x3f7abe893e953f35,0xbea1bf313f2cbf78,0x3f80bee63ef13f0e,0xbefcbf093f04bf80,0xbf133f7ebf7f3ec4,0x3f7fbecf3edb3f18,
0x3f6fbf423f463e48,0xbf4abe2f3e16bf71,0xbe603f77bf753f35,0x3f73bf393f3e3e79,0xbcc93f65bf623f55,0x3f5fbf583f5c3d49,0xbf51bdfb3dc9bf6d,0xbd973f6abf673f4e,
0x3eacbf783f7bbf35,0xbf7d3f2cbf22be95,0xbf803f18bf0ebec4,0x3f043edbbef13f7f,0xbf673f5cbf550000,0x3f4e3d49bdc93f62,0x3f3e3e16be483f6d,0x3e79bf713f75bf46,
0x3f71be793e483f35,0xbe16bf3e3f46bf75,0xbd49bf4e3f55bf6d,0xbf5c3f67bf623dc9,0xbedbbf043f0ebf80,0xbf183f80bf7f3ef1,0xbf2c3f7dbf7b3ec4,0x3f78beac3e953f22,
0x3f7ebf393f223e48,0xbf09bea13edbbf78,0xbd973f51bf623f6d,0x3f6fbf5f3f4ebd49,0xbf773ecfbe95bf0e,0x3e2f3f27bf3e3f7d,0x3ee6bf7a3f7fbf35,0xbf803f1dbf04beac,
0x3dfb3f31bf463f7b,0x3f58bf733f67be79,0xbf7f3f13bef1bec4,0x3eb83efcbf183f80,0x3e89bf6a3f75bf55,0xbf7c3f42bf2cbe16,0x3f65be603dc93f35,0x3cc9bf4a3f5cbf71,
0x3e483f0ebf353f80,0x3f55bf7b3f6dbec4,0x3f7bbf553f350000,0xbf0ebe483ec4bf6d,0xbe48bf0e3f35bf80,0xbf553f7bbf6d3ec4,0xbf7b3f55bf350000,0x3f0e3e48bec43f6d,
0xbf7b3f55bf358000,0x3f0e3e48bec43f6d,0x3e483f0ebf353f80,0x3f55bf7b3f6dbec4,0x3f7bbf553f358000,0xbf0ebe483ec4bf6d,0xbe48bf0e3f35bf80,0xbf553f7bbf6d3ec4,
0xbf4a3f80bf753f0e,0x3f58bea13d493f18,0xbf423e2f3dc9bf35,0xbeb83f5fbf783f67,0x3f77bf6a3f46be48,0xbf13bd973eacbf5c,0x3ee63e60bef13f6d,0x3f31bf7e3f7dbf2c,
0xbf1dbcc93e95bf55,0xbf093f73bf803f4e,0x3f27bf7c3f7fbf35,0xbf6f3efcbe79bedb,0x3e893ecfbf223f7b,0x3f51bf7f3f71bf04,0xbf653f7abf623ec4,0x3f39bdfbbe163f3e,
0xbf2c3e163e48bf35,0xbf043f67bf7f3f62,0xbf713f78bf553ec4,0x3f18bd49be953f46,0x3f80bf4e3f0e0000,0xbe79beac3f22bf75,0x3edbbf5c3f7bbf6d,0xbf7d3f3ebef1bdc9,
0x3f3ebf7d3f7bbf35,0xbf5c3edbbdc9bef1,0xbeacbe793f0ebf6d,0xbf4e3f80bf753f22,0xbd493f18bf553f80,0x3f78bf713f46be95,0x3f67bf043e483ec4,0x3e16bf2c3f62bf7f,
0x3f6abf7f3f62bf0e,0xbf1d3e2f3e79bf2c,0x3f58befc3dc93ec4,0x3ea1bf393f71bf7d,0x3cc93ee6bf463f7b,0x3f77bf7a3f4ebedb,0xbf513f7ebf753f35,0x3f42beb8bd493f04,
0x3ecf3d97bef13f55,0x3f4abf7c3f78bf3e,0xbf093f5fbf7f3f6d,0x3f73bf313eac3e16,0xbf803f65bf223e48,0x3e893e60bf183f67,0xbf133dfb3e95bf35,0xbf273f6fbf803f5c,
0x3e95bf223f6dbf80,0xbf7f3f62bf0e3e48,0xbef13dc93ec4bf35,0xbf463f75bf7b3f55,0xbf753f46bec40000,0xbdc93ef1bf553f7b,0xbf623f7fbf6d3f35,0x3f22be95be483f0e,
0x3f75bf463ec48000,0x3dc9bef13f55bf7b,0x3f62bf7f3f6dbf35,0xbf223e953e48bf0e,0x3e95bf223f6dbf80,0xbf7f3f62bf0e3e48,0xbef13dc93ec4bf35,0xbf463f75bf7b3f55,
0x3f51bf1d3dc93e48,0x3ee6bf313f78bf80,0x3eb8bd97bef13f35,0x3f5fbf7a3f71bf4e,0x3f58bf773f75bf55,0xbf273ecf3e16bedb,0x3f80bf733f22bec4,0xbdfbbe2f3f2cbf5c,
0xbf133f4abf7f3f7b,0x3f65bf393e793d49,0xbf6f3f7fbf623f35,0x3efcbe60beac3f18,0x3f09be89be953f0e,0x3f42bf6a3f7dbf67,0xbcc93ea1bf463f6d,0x3f7ebf7c3f3ebf04,
0xbf783f80bf553f35,0x3eacbe16bef13f22,0xbf4e3f67bf7b3f6d,0x3f2cbf04bdc93e95,0xbf5c3f3ebe480000,0xbedb3f18bf753f7f,0xbf7d3f71bf0e3ec4,0xbd493e79bf463f62,
0xbe793d493f0ebf35,0xbf713f7dbf623f46,0xbf183edb3e48bec4,0xbf3e3f5cbf7f3f75,0x3f04bf2c3f7bbf80,0xbf673f4ebe953dc9,0x3e16beac3f55bf6d,0xbf803f78bf223ef1,
0x3f42bf513f7fbf7b,0xbf313f1d3d49be16,0x3f5fbf6a3f75bf6d,0xbf093ee63e79beac,0x3f73bf7a3f62bf55,0xbeb83e893edbbf04,0x3f7ebf803f46bf35,0xbe2f3d973f18bf2c,
0x3f27bf13bdc93e48,0x3f39bf4a3f80bf7d,0x3efcbecfbe953ec4,0x3f58bf653f78bf71,0x3ea1be60bef13f0e,0x3f6fbf773f67bf5c,0x3dfbbcc9bf223f35,0x3f7cbf7f3f4ebf3e,
0x3f35bf35bf803f80,0xbf353f3500000000,0x3f35bf35bf803f80,0xbf353f3500000000,0x3f35bf35bf803f80,0xbf353f3500000000,0x3f35bf35bf803f80,0xbf353f3500000000,
0x3f35bf3580008000,0x3f35bf35bf803f80,0x3f35bf3580008000,0x3f35bf35bf803f80,0x3f35bf3580008000,0x3f35bf35bf803f80,0x3f35bf3580008000,0x3f35bf35bf803f80,
0xbea1be60bf75bf7b,0x3eb83e893f713f78,0xbdfbbcc9bf7fbf80,0x3e2f3d973f7d3f80,0xbf27bf13bf46bf55,0x3f313f1d3f3e3f4e,0xbefcbecfbf62bf6d,0x3f093ee63f5c3f67,
0xbf73bf7a3e953e48,0x3f6f3f77beacbe79,0xbf7ebf803dc98000,0x3f7c3f7fbe16bd49,0xbf42bf513f223f0e,0x3f393f4abf2cbf18,0xbf5fbf6a3ef13ec4,0x3f583f65bf04bedb,
0x3f5c3f3e3f0e3f35,0xbf67bf4ebef1bf22,0x3f7d3f713e483ec4,0xbf80bf78bdc9be95,0x3e793d493f7b3f80,0xbeacbe16bf75bf7f,0x3f183edb3f553f6d,0xbf2cbf04bf46bf62,
0x3f043f2cbf55bf35,0xbedbbf183f623f46,0x3e163eacbf7bbf6d,0xbd49be793f7f3f75,0x3f783f80be488000,0xbf71bf7d3e953dc9,0x3f4e3f67bf0ebec4,0xbf3ebf5c3f223ef1,
0xbf58bf773ef13e48,0x3f423f6abf18beac,0xbf80bf73bdc9bec4,0x3f7e3f7cbd493e79,0xbf51bf1dbf22bf55,0x3f653f393f043f3e,0xbeb8bd97bf75bf80,0x3efc3e603f673f7d,
0x3f093e893f623f7b,0xbf27becfbf4ebf71,0xbcc9bea13f7f3f6d,0xbdfb3e2fbf80bf78,0xbf13bf4a3f463f0e,0x3ee63f31bf5cbf2c,0xbf6fbf7f3e958000,0x3f5f3f7abedbbe16,
0x3ef13dc93f6d3f80,0xbf22be95bf55bf7b,0x3f753f463ec43f35,0xbf7fbf62be48bf0e,0x3f623f7fbec40000,0xbf46bf753f0e3e48,0x3e953f22bf6dbf35,0xbdc9bef13f7b3f55,
0x3f623f7fbec48000,0xbf46bf753f0e3e48,0x3e953f22bf6dbf35,0xbdc9bef13f7b3f55,0xbef1bdc9bf6dbf80,0x3f223e953f553f7b,0xbf75bf46bec4bf35,0x3f7f3f623e483f0e,
0xbf80bf65bdc9bf0e,0x3f773f7abe163eac,0xbf13bdfbbf62bf80,0x3f423eb83f3e3f78,0x3ecfbd973f753f7b,0xbf1dbe2fbf5cbf80,0xbf09bf5f3f463ec4,0x3ea13f39bf67bf18,
0x3cc9bee63f7f3f55,0xbe893e60bf7dbf71,0xbf51bf7e3ef18000,0x3f273f6fbf2cbe79,0x3f6a3f7fbe953e48,0xbf4abf7c3f043d49,0x3f583efc3f223f6d,0xbf73bf31bedbbf4e,
0x3d493f18bf7bbf35,0x3e79beac3f7f3f62,0xbf67bf04bf0ebf6d,0x3f7d3f3e3e953f46,0x3f2c3e163f553f80,0xbf5cbedbbf22bf75,0x3f713f78be483ec4,0xbf4ebf803ef1bdc9,
0xbf80bf4ebe48bf35,0x3f783f71bdc93ef1,0xbedbbf5c3f553ec4,0x3e163f2cbf75bf22,0x3f3e3f7dbf0e8000,0xbf04bf673f463e95,0xbeac3e79bf7bbf6d,0x3f183d493f623f7f,
0x3f773f6abdc93f0e,0xbf51bf7f3edbbe79,0x3ee6be603f753f6d,0xbf39bdfbbf4ebf80,0xbf4abf803ef1be48,0x3f093f73bf3ebe16,0xbf42be2fbf46bf80,0x3f6f3efc3f043f71,
0xbe893ecfbf7fbf55,0x3f13bd973f673f78,0x3f653f7abe953ec4,0xbf31bf7e3f18bd49,0x3f1dbcc93f623f7b,0xbf58bea1bf2cbf7d,0xbf27bf7c3f228000,0x3eb83f5fbf5cbeac,
0x3f553e483f353f80,0xbf7bbf0ebec4bf6d,0x3f0e3f7bbf350000,0xbe48bf553f6d3ec4,0xbf55be48bf35bf80,0x3f7b3f0e3ec43f6d,0xbf0ebf7b3f350000,0x3e483f55bf6dbec4,
0x3f0e3f7bbf358000,0xbe48bf553f6d3ec4,0xbf55be48bf35bf80,0x3f7b3f0e3ec43f6d,0xbf0ebf7b3f358000,0x3e483f55bf6dbec4,0x3f553e483f353f80,0xbf7bbf0ebec4bf6d,
0xbe89bf6a3f623e48,0xbe2f3f27bf80bf18,0xbf65be60bf22bf80,0x3f803f1d3e793f67,0xbdfb3f31bf7fbf0e,0x3f09bea13f713f5c,0x3f7f3f133e953f6d,0xbf6fbf5f3e16bf2c,
0x3f773ecf3ef13f7b,0xbf7cbf42bd49bf4e,0xbee6bf7a3f468000,0x3cc93f4abf78bedb,0xbf7ebf39bdc9bf55,0x3f583f73beac3f04,0x3d973f51bf75bec4,0x3eb8befc3f7d3f3e,
0xbf67bf5c3e48bf35,0x3f183f80bf223e95,0x3f3ebe163f553f6d,0xbf78beacbef1bf7f,0x3f713e793f0e3f80,0xbf7dbf2cbdc9bf62,0xbd493f4ebf7bbec4,0x3f04bedb3f753f46,
0x3edbbf043f7b3f35,0xbf4e3d49bf46bf75,0x3f2c3f7dbf0e3ec4,0xbe79bf713f623dc9,0x3eac3f78bf558000,0x3e16bf3e3f7f3ef1,0xbf80bf18be48bf6d,0x3f5c3f67be953f22,
0xbf80bee6be95bf7b,0x3f5f3f58be793f3e,0x3f133f7ebf223ec4,0xbd97bf6a3f713e16,0x3eb8bf273f7f3f0e,0xbf4a3e2fbf4ebf67,0xbf7abe89bef1bf80,0x3f733f39bd493f5c,
0xbcc9bf653f753e48,0xbefc3f09bf78bf2c,0xbf513dfbbf46bf6d,0x3f7f3ecf3eac3f7d,0x3f6f3f42bdc93f55,0xbf1dbf7c3f18bedb,0xbe60bf773f628000,0xbea13f31bf80bf04,
0x3f7f3e953ec43f80,0xbf62bf463e48bf55,0xbf223ef1bf6dbf35,0x3f753dc93f0e3f7b,0xbdc9bf753f6d0000,0xbef13f22bf7bbf0e,0x3f463f62bec43f35,0xbe95bf7f3f55be48,
0x3dc93f75bf6d8000,0x3ef1bf223f7b3f0e,0xbf46bf623ec4bf35,0x3e953f7fbf553e48,0x3f7f3e953ec43f80,0xbf62bf463e48bf55,0xbf223ef1bf6dbf35,0x3f753dc93f0e3f7b,
0x3f58be893f463f55,0xbf7fbeb8be79bf80,0xbf80bea1be95bf80,0x3f4a3f51beac3f4e,0xbe2fbf7e3f62be48,0xbee63f39bf7dbedb,0xbecf3f42bf7fbec4,0x3f5fbe603f3e3f5c,
0x3f093f77bf223f0e,0x3d97bf6f3f783d49,0x3cc9bf733f758000,0xbf1d3f13bf71bf18,0x3f7c3dfb3ef13f7b,0xbf65bf313e16bf67,0xbf6abf273dc9bf6d,0x3efc3f7abf2c3f04,
0x3f4ebedb3f553f35,0xbf80be79be95bf7f,0xbf043f3ebf7bbec4,0x3f71be163f223f62,0x3f7d3eac3e483f80,0xbf2cbf5c3ef1bf46,0xbf783d49bf0ebf6d,0x3f673f18bdc93f75,
0x3f183f67bf0e3f35,0x3d49bf783f75bdc9,0xbf5cbf2c3e48bf6d,0x3eac3f7dbf463ef1,0xbe163f71bf7b8000,0x3f3ebf043f623f22,0xbe79bf803f55bec4,0xbedb3f4ebf7fbe95,
0x3f73be603f223f55,0xbf6abefc3d49bf7d,0xbf7e3cc9bef1bf6d,0x3f513f27be793f71,0x3f7f3e2f3e953f7b,0xbf31bf4a3edbbf5c,0xbf77beb8bdc9bf80,0x3f093f65bf183f3e,
0x3ea13f7abf463f0e,0x3ecfbf5f3f803e16,0xbdfbbf803f62bec4,0xbf133f42bf78beac,0xbd973f7cbf753e48,0x3f39bf1d3f673f04,0x3e89bf6f3f7f8000,0xbf583ee6bf4ebf2c,
0x3f6d3ec400003f80,0xbec4bf6d3f35bf35,0xbf6dbec40000bf80,0x3ec43f6dbf353f35,0x3f6d3ec400003f80,0xbec4bf6d3f35bf35,0xbf6dbec40000bf80,0x3ec43f6dbf353f35,
0xbec43f6dbf808000,0x3f6dbec43f353f35,0x3ec4bf6d3f808000,0xbf6d3ec4bf35bf35,0xbec43f6dbf808000,0x3f6dbec43f353f35,0x3ec4bf6d3f808000,0xbf6d3ec4bf35bf35,
0x3f423f13be953f7b,0xbcc9bf7e3f67bf04,0xbf5fbecf3dc9bf80,0x3e603f73bf4e3f2c,0x3ee63f58bf223f55,0x3eb8bf773f80be16,0xbf1dbf393ef1bf6d,0xbe2f3f7fbf783eac,
0xbf273f51bf75be48,0x3f80bdfb3edb3f5c,0x3efcbf6a3f7f8000,0xbf7a3ea1bf18bf3e,0xbf653f09bf46bf0e,0x3f6f3e893d493f7d,0x3f4abf313f623ec4,0xbf7cbd97be79bf71,
0x3e163f71bf553f35,0x3f2cbf5c3f753dc9,0x3e79bf803f7bbec4,0xbf673f18bf46bef1,0x3f4e3edbbe483f80,0xbd49bf783f62bf22,0xbf04bf3e3f0ebf6d,0xbeac3f7dbf7f3e95,
0xbf7d3eacbf0ebf35,0x3f3e3f04be953f7f,0x3f783d493e483f6d,0xbedbbf4e3f22bf62,0xbf183f67bf7b8000,0x3f80be793ef13f46,0x3f5cbf2c3f553ec4,0xbf71be16bdc9bf75,
0xbf513f4abf62be48,0x3f733cc93e163f67,0x3eb8bf7f3f7fbec4,0xbf773f09bf2cbf04,0x3e603f5fbf463f55,0x3f27bf6a3f78bd49,0xbf39bee63e95bf80,0xbdfb3f7cbf713f18,
0xbf13bf1d3ef1bf7b,0xbea13f80bf7d3edb,0x3f6f3d973dc93f6d,0xbe89bf583f3ebf5c,0xbf7a3efcbf22bf0e,0x3f423ecfbe793f80,0x3f31bf653f758000,0xbf7e3e2fbeacbf4e,
0x3f223ef1bec43f80,0x3e95bf7f3f7bbf0e,0x3dc9bf753f6dbf35,0xbf623f46bf55be48,0xbf463f62bf6d0000,0x3f75bdc93e483f55,0x3f7fbe953ec43f35,0xbef1bf223f0ebf7b,
0xbf463f62bf6d8000,0x3f75bdc93e483f55,0x3f7fbe953ec43f35,0xbef1bf223f0ebf7b,0xbf22bef13ec4bf80,0xbe953f7fbf7b3f0e,0xbdc93f75bf6d3f35,0x3f62bf463f553e48,
0xbecf3f7fbf7f3f0e,0x3f7ebf133f183edb,0xbf09befc3ef1bf80,0xbee63f80bf803f04,0xbf31bea13e95bf7b,0xbe893f7abf783f2c,0x3f7cbf1d3f223ec4,0xbf27beb83eacbf7d,
0xbf6a3d97bdc9bf55,0x3dfb3f51bf4e3f67,0x3f58bf5f3f628000,0xbf653cc9bd49bf5c,0x3f39bf733f75be48,0xbf773e60be79bf3e,0x3e2f3f4abf463f6d,0x3f42bf6f3f71be16,
0xbf713e79be48bf35,0x3e163f3ebf463f75,0x3d493f4ebf553f6d,0x3f5cbf673f62bdc9,0x3edb3f04bf0e3f80,0x3f18bf803f7fbef1,0x3f2cbf7d3f7bbec4,0xbf783eacbe95bf22,
0x3eacbf783f7bbf35,0xbf7d3f2cbf22be95,0xbf803f18bf0ebec4,0x3f043edbbef13f7f,0xbf673f5cbf558000,0x3f4e3d49bdc93f62,0x3f3e3e16be483f6d,0x3e79bf713f75bf46,
0x3f1dbf803f7fbf0e,0xbf7a3ee6beacbf04,0x3f273e2fbe953f6d,0x3ecfbf773f7dbf3e,0xbf5f3f6fbf623e48,0x3f51bd97bd493f4e,0xbea1bf093f22bf80,0xbf393f7ebf783edb,
0x3f4abcc9bdc93f55,0x3e60bf653f71bf5c,0xbf423f7cbf753ec4,0x3f6abe893e163f2c,0xbefcbeb83ef1bf7b,0xbf133f7fbf803f18,0x3f73bf583f468000,0xbf31bdfb3e79bf67,
0x3e483f0ebf353f80,0x3f55bf7b3f6dbec4,0x3f7bbf553f350000,0xbf0ebe483ec4bf6d,0xbe48bf0e3f35bf80,0xbf553f7bbf6d3ec4,0xbf7b3f55bf350000,0x3f0e3e48bec43f6d,
0xbf7b3f55bf358000,0x3f0e3e48bec43f6d,0x3e483f0ebf353f80,0x3f55bf7b3f6dbec4,0x3f7bbf553f358000,0xbf0ebe483ec4bf6d,0xbe48bf0e3f35bf80,0xbf553f7bbf6d3ec4,
0xbf7e3f31bef1be48,0x3e603ee6bf2c3f7d,0xbd97bf133f46bf80,0xbf6a3f77bf5c3eac,0x3f5fbeb83dc93f0e,0x3e2fbf423f67bf78,0xbea13f58bf753f6d,0x3f80bf4a3f183d49,
0x3dfbbf393f62bf7b,0xbf7a3f65bf3e3e16,0x3f7fbf513f228000,0xbecfbe893f04bf71,0xbefc3f6fbf7f3f55,0x3f7cbf273edb3e79,0xbf733f09be95bec4,0x3cc93f1dbf4e3f80,
0x3f3ebf7d3f7bbf35,0xbf5c3edbbdc9bef1,0xbeacbe793f0ebf6d,0xbf4e3f80bf753f22,0xbd493f18bf553f80,0x3f78bf713f46be95,0x3f67bf043e483ec4,0x3e16bf2c3f62bf7f,
0x3f2cbe16be483f35,0x3f04bf673f7fbf62,0x3f71bf783f55bec4,0xbf183d493e95bf46,0xbf803f4ebf0e8000,0x3e793eacbf223f75,0xbedb3f5cbf7b3f6d,0x3f7dbf3e3ef13dc9,
0xbeb83f42bf753f7b,0x3f7ebf513f04bd49,0xbf7a3f77bf463ec4,0x3ee63cc9bedb3f4e,0xbf393ea13dc9bf0e,0xbefc3f58bf7d3f71,0x3e2fbf1d3f62bf80,0xbf7f3f6abf2c3e79,
0xbf6f3f27be95be48,0xbdfb3f13bf5c3f80,0xbe60be893f22bf6d,0xbf653f80bf673f18,0x3f31bf733f7fbf55,0xbf5f3f09be16beac,0x3f7cbf4a3ef18000,0xbd97becf3f3ebf78,
0xbe953f22bf6d3f80,0x3f7fbf623f0ebe48,0x3ef1bdc9bec43f35,0x3f46bf753f7bbf55,0x3f75bf463ec40000,0x3dc9bef13f55bf7b,0x3f62bf7f3f6dbf35,0xbf223e953e48bf0e,
0xbf753f46bec48000,0xbdc93ef1bf553f7b,0xbf623f7fbf6d3f35,0x3f22be95be483f0e,0xbe953f22bf6d3f80,0x3f7fbf623f0ebe48,0x3ef1bdc9bec43f35,0x3f46bf753f7bbf55,
0xbe2fbdfb3f22bf55,0xbf733f80bf5c3f2c,0x3ecfbf273f75bf80,0xbf773f58bedb3e16,0xbf7a3f5fbef13e48,0xbd973eb8bf4e3f71,0xbf313ee63dc9bec4,0xbf1d3f51bf803f78,
0x3f7cbf7e3f46bf0e,0xbea13cc93f04bf3e,0x3f6abf423e958000,0x3e89bf093f67bf7d,0x3e60befc3f62bf7b,0xbf7f3f6fbf183eac,0x3f39bf653f7fbf6d,0xbf4a3f13bd49be79,
0x3e79bd49bf0e3f35,0x3f71bf7d3f62bf46,0x3f18bedbbe483ec4,0x3f3ebf5c3f7fbf75,0xbf043f2cbf7b3f80,0x3f67bf4e3e95bdc9,0xbe163eacbf553f6d,0x3f80bf783f22bef1,
0xbf783f80bf553f35,0x3eacbe16bef13f22,0xbf4e3f67bf7b3f6d,0x3f2cbf04bdc93e95,0xbf5c3f3ebe488000,0xbedb3f18bf753f7f,0xbf7d3f71bf0e3ec4,0xbd493e79bf463f62,
0x3d97be2f3f46bf55,0xbf803f7ebf2c3f18,0x3e89beb83f62bf6d,0xbf7a3f73bf043edb,0x3ee6bf093f75bf7b,0xbf6a3f5fbeac3e79,0x3f1dbf313f7fbf80,0xbf513f42be163d49,
0x3f7fbf7c3f22bf0e,0x3cc9bdfb3f3ebf4e,0x3f77bf6f3ef1bec4,0x3e60bea13f5cbf67,0x3f65bf583e95be48,0x3ecfbefc3f71bf78,0x3f4abf393dc98000,0x3f13bf273f7dbf80,
0x3f35bf35bf803f80,0xbf353f3500000000,0x3f35bf35bf803f80,0xbf353f3500000000,0x3f35bf35bf803f80,0xbf353f3500000000,0x3f35bf35bf803f80,0xbf353f3500000000,
0x3f35bf3580008000,0x3f35bf35bf803f80,0x3f35bf3580008000,0x3f35bf35bf803f80,0x3f35bf3580008000,0x3f35bf35bf803f80,0x3f35bf3580008000,0x3f35bf35bf803f80,
0xbf65bf58bef1bf0e,0x3f6a3f5f3edb3f04,0xbf4abf39bf22bf35,0x3f513f423f183f2c,0xbf7fbf7cbdc9be48,0x3f803f7e3d493e16,0xbf77bf6fbe95bec4,0x3f7a3f733e793eac,
0xbee6bf093f623f55,0x3ecf3efcbf67bf5c,0xbf1dbf313f463f35,0x3f133f27bf4ebf3e,0xbd97be2f3f7f3f7b,0x3cc93dfbbf80bf7d,0xbe89beb83f753f6d,0x3e603ea1bf78bf71,
0x3f043f2cbf55bf35,0xbedbbf183f623f46,0x3e163eacbf7bbf6d,0xbd49be793f7f3f75,0x3f783f80be480000,0xbf71bf7d3e953dc9,0x3f4e3f67bf0ebec4,0xbf3ebf5c3f223ef1,
0xbf5cbf3ebf0ebf35,0x3f673f4e3ef13f22,0xbf7dbf71be48bec4,0x3f803f783dc93e95,0xbe79bd49bf7bbf80,0x3eac3e163f753f7f,0xbf18bedbbf55bf6d,0x3f2c3f043f463f62,
0x3f7a3f5f3e953f0e,0xbf7fbf6fbe16bedb,0x3f313ee63f463f6d,0xbf4abf13bf2cbf5c,0x3e2fbdfb3f7f3f7b,0xbea1bcc9bf78bf80,0xbecfbf273f623f35,0x3e893f09bf71bf4e,
0x3e603efcbf75bf55,0xbd97beb83f7d3f67,0x3f393f65bf22bec4,0xbf1dbf513f3e3f04,0x3f7c3f7ebdc93e48,0xbf73bf803e79bd49,0x3f6a3f423ef13f35,0xbf77bf58beacbf18,
0xbef1bdc9bf6dbf80,0x3f223e953f553f7b,0xbf75bf46bec4bf35,0x3f7f3f623e483f0e,0xbf62bf7f3ec40000,0x3f463f75bf0ebe48,0xbe95bf223f6d3f35,0x3dc93ef1bf7bbf55,
0xbf62bf7f3ec48000,0x3f463f75bf0ebe48,0xbe95bf223f6d3f35,0x3dc93ef1bf7bbf55,0x3ef13dc93f6d3f80,0xbf22be95bf55bf7b,0x3f753f463ec43f35,0xbf7fbf62be48bf0e,
0x3f313f73bf22be48,0xbefcbf583f4e3edb,0x3f7c3f4a3e953f35,0xbf7fbf6abd49bf04,0xbf6fbf27bef1bf55,0x3f7e3f513e793f2c,0xbe603e89bf7fbf6d,0x3ee6bcc93f713f7d,
0xbf39bea1bf46bf7b,0x3f5f3f093f183f67,0x3e2f3f1dbf75bf35,0x3d97becf3f803f5c,0xbeb8bf423f623f0e,0x3dfb3f13bf78bf3e,0xbf7abf773dc9bec4,0x3f653f80beac3e16,
0x3f803f4e3e483f35,0xbf78bf713dc9bef1,0x3edb3f5cbf55bec4,0xbe16bf2c3f753f22,0xbf3ebf7d3f0e0000,0x3f043f67bf46be95,0x3eacbe793f7b3f6d,0xbf18bd49bf62bf7f,
0x3d493f18bf7bbf35,0x3e79beac3f7f3f62,0xbf67bf04bf0ebf6d,0x3f7d3f3e3e953f46,0x3f2c3e163f553f80,0xbf5cbedbbf22bf75,0x3f713f78be483ec4,0xbf4ebf803ef1bdc9,
0x3f5f3eb83f223f7b,0xbf7cbf27beacbf5c,0xbea1bf583f623ec4,0xbcc93f1dbf7dbf2c,0xbf7ebf31be95bf55,0x3f7a3f65bd493f18,0xbd973f13bf7fbf35,0x3ecfbe893f783f67,
0x3efc3f6fbf46be48,0xbe2fbf423f713f04,0x3f733f093ef13f6d,0xbf80bf4abe16bf3e,0xbdfbbf393f753f0e,0xbe603ee6bf80bf4e,0xbf7fbf51bdc9bf35,0x3f6a3f77be793edb,
0x3f553e483f353f80,0xbf7bbf0ebec4bf6d,0x3f0e3f7bbf350000,0xbe48bf553f6d3ec4,0xbf55be48bf35bf80,0x3f7b3f0e3ec43f6d,0xbf0ebf7b3f350000,0x3e483f55bf6dbec4,
0x3f0e3f7bbf358000,0xbe48bf553f6d3ec4,0xbf55be48bf35bf80,0x3f7b3f0e3ec43f6d,0xbf0ebf7b3f358000,0x3e483f55bf6dbec4,0x3f553e483f353f80,0xbf7bbf0ebec4bf6d,
0x3efcbeb83f753f55,0xbf51bd97bf3ebf7d,0xbf73bf583dc9bf35,0x3f393f7ebf043eac,0xbf4abcc9bf46bf7b,0x3f7a3ee63edb3f78,0x3f423f7cbef13ec4,0xbecfbf773f4e3d49,
0x3f5f3f6fbe953f0e,0xbf13bf7f3f2cbe16,0x3ea1bf093f7f3f35,0xbf313dfbbf5cbf71,0xbf1dbf803f22be48,0x3e603f65bf67be79,0xbf273e2fbf62bf6d,0x3f6a3e893f183f80,
0x3edbbf043f7b3f35,0xbf4e3d49bf46bf75,0x3f2c3f7dbf0e3ec4,0xbe79bf713f623dc9,0x3eac3f78bf550000,0x3e16bf3e3f7f3ef1,0xbf80bf18be48bf6d,0x3f5c3f67be953f22,
0x3f673f5cbe483f35,0xbf18bf803f22be95,0xbf3e3e16bf55bf6d,0x3f783eac3ef13f7f,0xbf71be79bf0ebf80,0x3f7d3f2c3dc93f62,0x3d49bf4e3f7b3ec4,0xbf043edbbf75bf46,
0x3f31bea13f623f55,0xbf77be60bf04bf80,0xbf7cbf1dbdc9bf6d,0x3f423f6fbedb3f18,0x3ecf3f7fbf463e48,0x3dfbbf513f7d3eac,0x3f09befc3f753f35,0xbf65bcc9bf2cbf78,
0x3f393f73bef13f0e,0xbe89bf7a3f5cbd49,0x3e2fbf4a3f7f3ec4,0xbf273eb8bf67bf4e,0xbf6abd97bf22bf7b,0x3f7e3f133e163f71,0x3f583f5fbe953f35,0xbee6bf803f3ebe79,
0xbf7fbe95bec4bf80,0x3f623f46be483f55,0x3f22bef13f6d3f35,0xbf75bdc9bf0ebf7b,0x3dc93f75bf6d0000,0x3ef1bf223f7b3f0e,0xbf46bf623ec4bf35,0x3e953f7fbf553e48,
0xbdc9bf753f6d8000,0xbef13f22bf7bbf0e,0x3f463f62bec43f35,0xbe95bf7f3f55be48,0xbf7fbe95bec4bf80,0x3f623f46be483f55,0x3f22bef13f6d3f35,0xbf75bdc9bf0ebf7b,
0xbf7abefcbdc9bf7b,0x3f273f6abf043f2c,0x3f313f65bef13f35,0xbdfbbf7c3f67be16,0xbf133f1dbf75bf0e,0x3f73bcc93f183f71,0x3f6fbd973f223f6d,0xbf77bf09bd49bf78,
0x3e60bf5f3f7f3e48,0xbf423ecfbf5cbf3e,0xbf393ee6bf62bf35,0x3f7e3e2f3edb3f7d,0xbf51bf4a3e95bf55,0x3ea13f80bf4e3eac,0x3eb83f7fbf463ec4,0x3e89bf583f803e79,
0xbf18bf673f0ebf35,0xbd493f78bf753dc9,0x3f5c3f2cbe483f6d,0xbeacbf7d3f46bef1,0x3e16bf713f7b0000,0xbf3e3f04bf62bf22,0x3e793f80bf553ec4,0x3edbbf4e3f7f3e95,
0x3f4ebedb3f553f35,0xbf80be79be95bf7f,0xbf043f3ebf7bbec4,0x3f71be163f223f62,0x3f7d3eac3e483f80,0xbf2cbf5c3ef1bf46,0xbf783d49bf0ebf6d,0x3f673f18bdc93f75,
0x3ee6bf583f7f3e48,0xbf6f3e89bf2cbf4e,0xbf1d3f39bf75bec4,0x3f7cbd973f043f67,0x3f42bf133f623f0e,0xbf80bdfbbeacbf78,0xbf5f3ecfbf46bf35,0x3f7a3ea13e163f80,
0x3f653f09bdc93f7b,0xbeb8bf773f3ebf18,0xbf4abf313e95bf6d,0x3e2f3f7fbf5c3edb,0x3f273f51bef13f55,0x3cc9bf7e3f71be79,0xbefcbf6a3f22bf35,0xbe603f73bf7d3d49,
0x3f6d3ec400003f80,0xbec4bf6d3f35bf35,0xbf6dbec40000bf80,0x3ec43f6dbf353f35,0x3f6d3ec400003f80,0xbec4bf6d3f35bf35,0xbf6dbec40000bf80,0x3ec43f6dbf353f35,
0xbec43f6dbf808000,0x3f6dbec43f353f35,0x3ec4bf6d3f808000,0xbf6d3ec4bf35bf35,0xbec43f6dbf808000,0x3f6dbec43f353f35,0x3ec4bf6d3f808000,0xbf6d3ec4bf35bf35,
0x3d973f7cbf623f0e,0x3f31bf4a3f713e79,0xbe89bf6f3f46bf35,0xbf093f65bf7dbd49,0xbea13f7abf7f3e48,0x3f6abefc3f3e3f18,0x3dfbbf803f75bec4,0xbf513f27bf5cbedb,
0xbf7f3e2fbef1bf55,0x3f393f1dbeac3f78,0x3f77beb83f223f35,0xbf58bee63e16bf80,0xbf73be60bdc9bf7b,0x3ecf3f5fbf2c3f4e,0x3f7e3cc93e953f6d,0xbf13bf423f04bf67,
0xbf7d3eacbf0ebf35,0x3f3e3f04be953f7f,0x3f783d493e483f6d,0xbedbbf4e3f22bf62,0xbf183f67bf7b0000,0x3f80be793ef13f46,0x3f5cbf2c3f553ec4,0xbf71be16bdc9bf75,
0xbe16bf713f55bf35,0xbf2c3f5cbf75bdc9,0xbe793f80bf7b3ec4,0x3f67bf183f463ef1,0xbf4ebedb3e48bf80,0x3d493f78bf623f22,0x3f043f3ebf0e3f6d,0x3eacbf7d3f7fbe95,
0x3e2fbf7e3f75bf0e,0xbf653f31bf4ebeac,0x3ecf3f42bf223f6d,0x3efcbf7a3f80be79,0xbf58be893dc9bf7b,0x3d973f6fbf5c3f3e,0x3f80bea13ef13f35,0xbf1dbf133edbbf7d,
0x3f7cbdfb3e953f55,0xbee6bf393f18bf71,0xbf6a3f27bf46bec4,0x3f5f3e60bd493f78,0x3f09bf773f7fbe48,0xbf7f3eb8bf04bf2c,0x3cc93f73bf623f35,0x3f4abf513f673e16,
0xbf22bef13ec4bf80,0xbe953f7fbf7b3f0e,0xbdc93f75bf6d3f35,0x3f62bf463f553e48,0x3f46bf623f6d0000,0xbf753dc9be48bf55,0xbf7f3e95bec4bf35,0x3ef13f22bf0e3f7b,
0x3f46bf623f6d8000,0xbf753dc9be48bf55,0xbf7f3e95bec4bf35,0x3ef13f22bf0e3f7b,0x3f223ef1bec43f80,0x3e95bf7f3f7bbf0e,0x3dc9bf753f6dbf35,0xbf623f46bf55be48,
0x3f6fbf423f463e48,0xbf4abe2f3e16bf71,0xbe603f77bf753f35,0x3f73bf393f3e3e79,0xbcc93f65bf623f55,0x3f5fbf583f5c3d49,0xbf51bdfb3dc9bf6d,0xbd973f6abf673f4e,
0x3eb83f27bf223f7b,0x3f1dbf7c3f7dbeac,0xbf7a3e89be95bf35,0x3ea13f31bf2c3f78,0xbf803ee6bef1bf0e,0x3efc3f09bf043f80,0x3f13bf7e3f7fbec4,0xbf7f3ecfbedbbf18,
0xbeac3f78bf7b3f35,0x3f7dbf2c3f223e95,0x3f80bf183f0e3ec4,0xbf04bedb3ef1bf7f,0x3f67bf5c3f550000,0xbf4ebd493dc9bf62,0xbf3ebe163e48bf6d,0xbe793f71bf753f46,
0xbf713e79be48bf35,0x3e163f3ebf463f75,0x3d493f4ebf553f6d,0x3f5cbf673f62bdc9,0x3edb3f04bf0e3f80,0x3f18bf803f7fbef1,0x3f2cbf7d3f7bbec4,0xbf783eacbe95bf22,
0xbdfbbf313f46bf7b,0xbf583f73bf673e79,0x3f7fbf133ef13ec4,0xbeb8befc3f18bf80,0xbe893f6abf753f55,0x3f7cbf423f2c3e16,0xbf653e60bdc9bf35,0xbcc93f4abf5c3f71,
0x3f7ebf393f223e48,0xbf09bea13edbbf78,0xbd973f51bf623f6d,0x3f6fbf5f3f4ebd49,0xbf773ecfbe95bf0e,0x3e2f3f27bf3e3f7d,0x3ee6bf7a3f7fbf35,0xbf803f1dbf04beac,
0x3e483f0ebf353f80,0x3f55bf7b3f6dbec4,0x3f7bbf553f350000,0xbf0ebe483ec4bf6d,0xbe48bf0e3f35bf80,0xbf553f7bbf6d3ec4,0xbf7b3f55bf350000,0x3f0e3e48bec43f6d,
0xbf7b3f55bf358000,0x3f0e3e48bec43f6d,0x3e483f0ebf353f80,0x3f55bf7b3f6dbec4,0x3f7bbf553f358000,0xbf0ebe483ec4bf6d,0xbe48bf0e3f35bf80,0xbf553f7bbf6d3ec4,
0xbf1dbcc93e95bf55,0xbf093f73bf803f4e,0x3f27bf7c3f7fbf35,0xbf6f3efcbe79bedb,0x3e893ecfbf223f7b,0x3f51bf7f3f71bf04,0xbf653f7abf623ec4,0x3f39bdfbbe163f3e,
0x3f4abf803f75bf0e,0xbf583ea1bd49bf18,0x3f42be2fbdc93f35,0x3eb8bf5f3f78bf67,0xbf773f6abf463e48,0x3f133d97beac3f5c,0xbee6be603ef1bf6d,0xbf313f7ebf7d3f2c,
0x3f2cbe16be483f35,0x3f04bf673f7fbf62,0x3f71bf783f55bec4,0xbf183d493e95bf46,0xbf803f4ebf0e0000,0x3e793eacbf223f75,0xbedb3f5cbf7b3f6d,0x3f7dbf3e3ef13dc9,
0xbf3e3f7dbf7b3f35,0x3f5cbedb3dc93ef1,0x3eac3e79bf0e3f6d,0x3f4ebf803f75bf22,0x3d49bf183f55bf80,0xbf783f71bf463e95,0xbf673f04be48bec4,0xbe163f2cbf623f7f,
0xbecfbd973ef1bf55,0xbf4a3f7cbf783f3e,0x3f09bf5f3f7fbf6d,0xbf733f31beacbe16,0x3f80bf653f22be48,0xbe89be603f18bf67,0x3f13bdfbbe953f35,0x3f27bf6f3f80bf5c,
0x3f6abf7f3f62bf0e,0xbf1d3e2f3e79bf2c,0x3f58befc3dc93ec4,0x3ea1bf393f71bf7d,0x3cc93ee6bf463f7b,0x3f77bf7a3f4ebedb,0xbf513f7ebf753f35,0x3f42beb8bd493f04,
0x3e95bf223f6dbf80,0xbf7f3f62bf0e3e48,0xbef13dc93ec4bf35,0xbf463f75bf7b3f55,0xbf753f46bec40000,0xbdc93ef1bf553f7b,0xbf623f7fbf6d3f35,0x3f22be95be483f0e,
0x3f75bf463ec48000,0x3dc9bef13f55bf7b,0x3f62bf7f3f6dbf35,0xbf223e953e48bf0e,0x3e95bf223f6dbf80,0xbf7f3f62bf0e3e48,0xbef13dc93ec4bf35,0xbf463f75bf7b3f55,
0xbf133f4abf7f3f7b,0x3f65bf393e793d49,0xbf6f3f7fbf623f35,0x3efcbe60beac3f18,0x3f09be89be953f0e,0x3f42bf6a3f7dbf67,0xbcc93ea1bf463f6d,0x3f7ebf7c3f3ebf04,
0xbf513f1dbdc9be48,0xbee63f31bf783f80,0xbeb83d973ef1bf35,0xbf5f3f7abf713f4e,0xbf583f77bf753f55,0x3f27becfbe163edb,0xbf803f73bf223ec4,0x3dfb3e2fbf2c3f5c,
0x3f78bf803f55bf35,0xbeac3e163ef1bf22,0x3f4ebf673f7bbf6d,0xbf2c3f043dc9be95,0x3f5cbf3e3e480000,0x3edbbf183f75bf7f,0x3f7dbf713f0ebec4,0x3d49be793f46bf62,
0x3e79bd49bf0e3f35,0x3f71bf7d3f62bf46,0x3f18bedbbe483ec4,0x3f3ebf5c3f7fbf75,0xbf043f2cbf7b3f80,0x3f67bf4e3e95bdc9,0xbe163eacbf553f6d,0x3f80bf783f22bef1,
0xbf273f133dc9be48,0xbf393f4abf803f7d,0xbefc3ecf3e95bec4,0xbf583f65bf783f71,0xbea13e603ef1bf0e,0xbf6f3f77bf673f5c,0xbdfb3cc93f22bf35,0xbf7c3f7fbf4e3f3e,
0x3f42bf513f7fbf7b,0xbf313f1d3d49be16,0x3f5fbf6a3f75bf6d,0xbf093ee63e79beac,0x3f73bf7a3f62bf55,0xbeb83e893edbbf04,0x3f7ebf803f46bf35,0xbe2f3d973f18bf2c,
0x3f35bf35bf803f80,0xbf353f3500000000,0x3f35bf35bf803f80,0xbf353f3500000000,0x3f35bf35bf803f80,0xbf353f3500000000,0x3f35bf35bf803f80,0xbf353f3500000000,
0x3f35bf3580008000,0x3f35bf35bf803f80,0x3f35bf3580008000,0x3f35bf35bf803f80,0x3f35bf3580008000,0x3f35bf35bf803f80,0x3f35bf3580008000,0x3f35bf35bf803f80,
0xbf73bf7a3e953e48,0x3f6f3f77beacbe79,0xbf7ebf803dc90000,0x3f7c3f7fbe16bd49,0xbf42bf513f223f0e,0x3f393f4abf2cbf18,0xbf5fbf6a3ef13ec4,0x3f583f65bf04bedb,
0x3ea13e603f753f7b,0xbeb8be89bf71bf78,0x3dfb3cc93f7f3f80,0xbe2fbd97bf7dbf80,0x3f273f133f463f55,0xbf31bf1dbf3ebf4e,0x3efc3ecf3f623f6d,0xbf09bee6bf5cbf67,
0xbf5cbf3ebf0ebf35,0x3f673f4e3ef13f22,0xbf7dbf71be48bec4,0x3f803f783dc93e95,0xbe79bd49bf7bbf80,0x3eac3e163f753f7f,0xbf18bedbbf55bf6d,0x3f2c3f043f463f62,
0xbf04bf2c3f553f35,0x3edb3f18bf62bf46,0xbe16beac3f7b3f6d,0x3d493e79bf7fbf75,0xbf78bf803e488000,0x3f713f7dbe95bdc9,0xbf4ebf673f0e3ec4,0x3f3e3f5cbf22bef1,
0xbf09be89bf62bf7b,0x3f273ecf3f4e3f71,0x3cc93ea1bf7fbf6d,0x3dfbbe2f3f803f78,0x3f133f4abf46bf0e,0xbee6bf313f5c3f2c,0x3f6f3f7fbe950000,0xbf5fbf7a3edb3e16,
0xbf58bf773ef13e48,0x3f423f6abf18beac,0xbf80bf73bdc9bec4,0x3f7e3f7cbd493e79,0xbf51bf1dbf22bf55,0x3f653f393f043f3e,0xbeb8bd97bf75bf80,0x3efc3e603f673f7d,
0x3ef13dc93f6d3f80,0xbf22be95bf55bf7b,0x3f753f463ec43f35,0xbf7fbf62be48bf0e,0x3f623f7fbec40000,0xbf46bf753f0e3e48,0x3e953f22bf6dbf35,0xbdc9bef13f7b3f55,
0x3f623f7fbec48000,0xbf46bf753f0e3e48,0x3e953f22bf6dbf35,0xbdc9bef13f7b3f55,0xbef1bdc9bf6dbf80,0x3f223e953f553f7b,0xbf75bf46bec4bf35,0x3f7f3f623e483f0e,
0x3cc9bee63f7f3f55,0xbe893e60bf7dbf71,0xbf51bf7e3ef10000,0x3f273f6fbf2cbe79,0x3f6a3f7fbe953e48,0xbf4abf7c3f043d49,0x3f583efc3f223f6d,0xbf73bf31bedbbf4e,
0x3f803f653dc93f0e,0xbf77bf7a3e16beac,0x3f133dfb3f623f80,0xbf42beb8bf3ebf78,0xbecf3d97bf75bf7b,0x3f1d3e2f3f5c3f80,0x3f093f5fbf46bec4,0xbea1bf393f673f18,
0xbd49bf183f7b3f35,0xbe793eacbf7fbf62,0x3f673f043f0e3f6d,0xbf7dbf3ebe95bf46,0xbf2cbe16bf55bf80,0x3f5c3edb3f223f75,0xbf71bf783e48bec4,0x3f4e3f80bef13dc9,
0x3f803f4e3e483f35,0xbf78bf713dc9bef1,0x3edb3f5cbf55bec4,0xbe16bf2c3f753f22,0xbf3ebf7d3f0e8000,0x3f043f67bf46be95,0x3eacbe793f7b3f6d,0xbf18bd49bf62bf7f,
0x3e89becf3f7f3f55,0xbf133d97bf67bf78,0xbf65bf7a3e95bec4,0x3f313f7ebf183d49,0xbf1d3cc9bf62bf7b,0x3f583ea13f2c3f7d,0x3f273f7cbf220000,0xbeb8bf5f3f5c3eac,
0x3f773f6abdc93f0e,0xbf51bf7f3edbbe79,0x3ee6be603f753f6d,0xbf39bdfbbf4ebf80,0xbf4abf803ef1be48,0x3f093f73bf3ebe16,0xbf42be2fbf46bf80,0x3f6f3efc3f043f71,
0x3f553e483f353f80,0xbf7bbf0ebec4bf6d,0x3f0e3f7bbf350000,0xbe48bf553f6d3ec4,0xbf55be48bf35bf80,0x3f7b3f0e3ec43f6d,0xbf0ebf7b3f350000,0x3e483f55bf6dbec4,
0x3f0e3f7bbf358000,0xbe48bf553f6d3ec4,0xbf55be48bf35bf80,0x3f7b3f0e3ec43f6d,0xbf0ebf7b3f358000,0x3e483f55bf6dbec4,0x3f553e483f353f80,0xbf7bbf0ebec4bf6d,
0x3f773ecf3ef13f7b,0xbf7cbf42bd49bf4e,0xbee6bf7a3f460000,0x3cc93f4abf78bedb,0xbf7ebf39bdc9bf55,0x3f583f73beac3f04,0x3d973f51bf75bec4,0x3eb8befc3f7d3f3e,
0x3e893f6abf62be48,0x3e2fbf273f803f18,0x3f653e603f223f80,0xbf80bf1dbe79bf67,0x3dfbbf313f7f3f0e,0xbf093ea1bf71bf5c,0xbf7fbf13be95bf6d,0x3f6f3f5fbe163f2c,
0x3f673f5cbe483f35,0xbf18bf803f22be95,0xbf3e3e16bf55bf6d,0x3f783eac3ef13f7f,0xbf71be79bf0ebf80,0x3f7d3f2c3dc93f62,0x3d49bf4e3f7b3ec4,0xbf043edbbf75bf46,
0xbedb3f04bf7bbf35,0x3f4ebd493f463f75,0xbf2cbf7d3f0ebec4,0x3e793f71bf62bdc9,0xbeacbf783f558000,0xbe163f3ebf7fbef1,0x3f803f183e483f6d,0xbf5cbf673e95bf22,
0x3cc93f65bf75be48,0x3efcbf093f783f2c,0x3f51bdfb3f463f6d,0xbf7fbecfbeacbf7d,0xbf6fbf423dc9bf55,0x3f1d3f7cbf183edb,0x3e603f77bf620000,0x3ea1bf313f803f04,
0xbf80bee6be95bf7b,0x3f5f3f58be793f3e,0x3f133f7ebf223ec4,0xbd97bf6a3f713e16,0x3eb8bf273f7f3f0e,0xbf4a3e2fbf4ebf67,0xbf7abe89bef1bf80,0x3f733f39bd493f5c,
0x3f7f3e953ec43f80,0xbf62bf463e48bf55,0xbf223ef1bf6dbf35,0x3f753dc93f0e3f7b,0xbdc9bf753f6d0000,0xbef13f22bf7bbf0e,0x3f463f62bec43f35,0xbe95bf7f3f55be48,
0x3dc93f75bf6d8000,0x3ef1bf223f7b3f0e,0xbf46bf623ec4bf35,0x3e953f7fbf553e48,0x3f7f3e953ec43f80,0xbf62bf463e48bf55,0xbf223ef1bf6dbf35,0x3f753dc93f0e3f7b,
0x3f093f77bf223f0e,0x3d97bf6f3f783d49,0x3cc9bf733f750000,0xbf1d3f13bf71bf18,0x3f7c3dfb3ef13f7b,0xbf65bf313e16bf67,0xbf6abf273dc9bf6d,0x3efc3f7abf2c3f04,
0xbf583e89bf46bf55,0x3f7f3eb83e793f80,0x3f803ea13e953f80,0xbf4abf513eacbf4e,0x3e2f3f7ebf623e48,0x3ee6bf393f7d3edb,0x3ecfbf423f7f3ec4,0xbf5f3e60bf3ebf5c,
0xbf4e3edbbf55bf35,0x3f803e793e953f7f,0x3f04bf3e3f7b3ec4,0xbf713e16bf22bf62,0xbf7dbeacbe48bf80,0x3f2c3f5cbef13f46,0x3f78bd493f0e3f6d,0xbf67bf183dc9bf75,
0xbf18bf673f0ebf35,0xbd493f78bf753dc9,0x3f5c3f2cbe483f6d,0xbeacbf7d3f46bef1,0x3e16bf713f7b8000,0xbf3e3f04bf62bf22,0x3e793f80bf553ec4,0x3edbbf4e3f7f3e95,
0xbea1bf7a3f46bf0e,0xbecf3f5fbf80be16,0x3dfb3f80bf623ec4,0x3f13bf423f783eac,0x3d97bf7c3f75be48,0xbf393f1dbf67bf04,0xbe893f6fbf7f0000,0x3f58bee63f4e3f2c,
0x3f73be603f223f55,0xbf6abefc3d49bf7d,0xbf7e3cc9bef1bf6d,0x3f513f27be793f71,0x3f7f3e2f3e953f7b,0xbf31bf4a3edbbf5c,0xbf77beb8bdc9bf80,0x3f093f65bf183f3e,
0x3f6d3ec400003f80,0xbec4bf6d3f35bf35,0xbf6dbec40000bf80,0x3ec43f6dbf353f35,0x3f6d3ec400003f80,0xbec4bf6d3f35bf35,0xbf6dbec40000bf80,0x3ec43f6dbf353f35,
0xbec43f6dbf808000,0x3f6dbec43f353f35,0x3ec4bf6d3f808000,0xbf6d3ec4bf35bf35,0xbec43f6dbf808000,0x3f6dbec43f353f35,0x3ec4bf6d3f808000,0xbf6d3ec4bf35bf35,
0xbf273f51bf75be48,0x3f80bdfb3edb3f5c,0x3efcbf6a3f7f0000,0xbf7a3ea1bf18bf3e,0xbf653f09bf46bf0e,0x3f6f3e893d493f7d,0x3f4abf313f623ec4,0xbf7cbd97be79bf71,
0xbf42bf133e95bf7b,0x3cc93f7ebf673f04,0x3f5f3ecfbdc93f80,0xbe60bf733f4ebf2c,0xbee6bf583f22bf55,0xbeb83f77bf803e16,0x3f1d3f39bef13f6d,0x3e2fbf7f3f78beac,
0xbe16bf713f55bf35,0xbf2c3f5cbf75bdc9,0xbe793f80bf7b3ec4,0x3f67bf183f463ef1,0xbf4ebedb3e48bf80,0x3d493f78bf623f22,0x3f043f3ebf0e3f6d,0x3eacbf7d3f7fbe95,
0x3f7dbeac3f0e3f35,0xbf3ebf043e95bf7f,0xbf78bd49be48bf6d,0x3edb3f4ebf223f62,0x3f18bf673f7b8000,0xbf803e79bef1bf46,0xbf5c3f2cbf55bec4,0x3f713e163dc93f75,
0x3f133f1dbef13f7b,0x3ea1bf803f7dbedb,0xbf6fbd97bdc9bf6d,0x3e893f58bf3e3f5c,0x3f7abefc3f223f0e,0xbf42becf3e79bf80,0xbf313f65bf750000,0x3f7ebe2f3eac3f4e,
0xbf513f4abf62be48,0x3f733cc93e163f67,0x3eb8bf7f3f7fbec4,0xbf773f09bf2cbf04,0x3e603f5fbf463f55,0x3f27bf6a3f78bd49,0xbf39bee63e95bf80,0xbdfb3f7cbf713f18,
0x3f223ef1bec43f80,0x3e95bf7f3f7bbf0e,0x3dc9bf753f6dbf35,0xbf623f46bf55be48,0xbf463f62bf6d0000,0x3f75bdc93e483f55,0x3f7fbe953ec43f35,0xbef1bf223f0ebf7b,
0xbf463f62bf6d8000,0x3f75bdc93e483f55,0x3f7fbe953ec43f35,0xbef1bf223f0ebf7b,0xbf22bef13ec4bf80,0xbe953f7fbf7b3f0e,0xbdc93f75bf6d3f35,0x3f62bf463f553e48,
0xbf6a3d97bdc9bf55,0x3dfb3f51bf4e3f67,0x3f58bf5f3f620000,0xbf653cc9bd49bf5c,0x3f39bf733f75be48,0xbf773e60be79bf3e,0x3e2f3f4abf463f6d,0x3f42bf6f3f71be16,
0x3ecfbf7f3f7fbf0e,0xbf7e3f13bf18bedb,0x3f093efcbef13f80,0x3ee6bf803f80bf04,0x3f313ea1be953f7b,0x3e89bf7a3f78bf2c,0xbf7c3f1dbf22bec4,0x3f273eb8beac3f7d,
0x3f71be793e483f35,0xbe16bf3e3f46bf75,0xbd49bf4e3f55bf6d,0xbf5c3f67bf623dc9,0xbedbbf043f0ebf80,0xbf183f80bf7f3ef1,0xbf2c3f7dbf7b3ec4,0x3f78beac3e953f22,
0xbeac3f78bf7b3f35,0x3f7dbf2c3f223e95,0x3f80bf183f0e3ec4,0xbf04bedb3ef1bf7f,0x3f67bf5c3f558000,0xbf4ebd493dc9bf62,0xbf3ebe163e48bf6d,0xbe793f71bf753f46,
0xbf4a3cc93dc9bf55,0xbe603f65bf713f5c,0x3f42bf7c3f75bec4,0xbf6a3e89be16bf2c,0x3efc3eb8bef13f7b,0x3f13bf7f3f80bf18,0xbf733f58bf460000,0x3f313dfbbe793f67,
0x3f1dbf803f7fbf0e,0xbf7a3ee6beacbf04,0x3f273e2fbe953f6d,0x3ecfbf773f7dbf3e,0xbf5f3f6fbf623e48,0x3f51bd97bd493f4e,0xbea1bf093f22bf80,0xbf393f7ebf783edb,
0x3e483f0ebf353f80,0x3f55bf7b3f6dbec4,0x3f7bbf553f350000,0xbf0ebe483ec4bf6d,0xbe48bf0e3f35bf80,0xbf553f7bbf6d3ec4,0xbf7b3f55bf350000,0x3f0e3e48bec43f6d,
0xbf7b3f55bf358000,0x3f0e3e48bec43f6d,0x3e483f0ebf353f80,0x3f55bf7b3f6dbec4,0x3f7bbf553f358000,0xbf0ebe483ec4bf6d,0xbe48bf0e3f35bf80,0xbf553f7bbf6d3ec4,
0x3dfbbf393f62bf7b,0xbf7a3f65bf3e3e16,0x3f7fbf513f220000,0xbecfbe893f04bf71,0xbefc3f6fbf7f3f55,0x3f7cbf273edb3e79,0xbf733f09be95bec4,0x3cc93f1dbf4e3f80,
0x3f7ebf313ef13e48,0xbe60bee63f2cbf7d,0x3d973f13bf463f80,0x3f6abf773f5cbeac,0xbf5f3eb8bdc9bf0e,0xbe2f3f42bf673f78,0x3ea1bf583f75bf6d,0xbf803f4abf18bd49,
0xbf3e3f7dbf7b3f35,0x3f5cbedb3dc93ef1,0x3eac3e79bf0e3f6d,0x3f4ebf803f75bf22,0x3d49bf183f55bf80,0xbf783f71bf463e95,0xbf673f04be48bec4,0xbe163f2cbf623f7f,
0xbf2c3e163e48bf35,0xbf043f67bf7f3f62,0xbf713f78bf553ec4,0x3f18bd49be953f46,0x3f80bf4e3f0e8000,0xbe79beac3f22bf75,0x3edbbf5c3f7bbf6d,0xbf7d3f3ebef1bdc9,
0x3f6fbf273e953e48,0x3dfbbf133f5cbf80,0x3e603e89bf223f6d,0x3f65bf803f67bf18,0xbf313f73bf7f3f55,0x3f5fbf093e163eac,0xbf7c3f4abef10000,0x3d973ecfbf3e3f78,
0xbeb83f42bf753f7b,0x3f7ebf513f04bd49,0xbf7a3f77bf463ec4,0x3ee63cc9bedb3f4e,0xbf393ea13dc9bf0e,0xbefc3f58bf7d3f71,0x3e2fbf1d3f62bf80,0xbf7f3f6abf2c3e79,
0xbe953f22bf6d3f80,0x3f7fbf623f0ebe48,0x3ef1bdc9bec43f35,0x3f46bf753f7bbf55,0x3f75bf463ec40000,0x3dc9bef13f55bf7b,0x3f62bf7f3f6dbf35,0xbf223e953e48bf0e,
0xbf753f46bec48000,0xbdc93ef1bf553f7b,0xbf623f7fbf6d3f35,0x3f22be95be483f0e,0xbe953f22bf6d3f80,0x3f7fbf623f0ebe48,0x3ef1bdc9bec43f35,0x3f46bf753f7bbf55,
0x3f7cbf7e3f46bf0e,0xbea13cc93f04bf3e,0x3f6abf423e950000,0x3e89bf093f67bf7d,0x3e60befc3f62bf7b,0xbf7f3f6fbf183eac,0x3f39bf653f7fbf6d,0xbf4a3f13bd49be79,
0x3e2f3dfbbf223f55,0x3f73bf803f5cbf2c,0xbecf3f27bf753f80,0x3f77bf583edbbe16,0x3f7abf5f3ef1be48,0x3d97beb83f4ebf71,0x3f31bee6bdc93ec4,0x3f1dbf513f80bf78,
0xbe793d493f0ebf35,0xbf713f7dbf623f46,0xbf183edb3e48bec4,0xbf3e3f5cbf7f3f75,0x3f04bf2c3f7bbf80,0xbf673f4ebe953dc9,0x3e16beac3f55bf6d,0xbf803f78bf223ef1,
0x3f78bf803f55bf35,0xbeac3e163ef1bf22,0x3f4ebf673f7bbf6d,0xbf2c3f043dc9be95,0x3f5cbf3e3e488000,0x3edbbf183f75bf7f,0x3f7dbf713f0ebec4,0x3d49be793f46bf62,
0xbf7f3f7cbf223f0e,0xbcc93dfbbf3e3f4e,0xbf773f6fbef13ec4,0xbe603ea1bf5c3f67,0xbf653f58be953e48,0xbecf3efcbf713f78,0xbf4a3f39bdc90000,0xbf133f27bf7d3f80,
0x3d97be2f3f46bf55,0xbf803f7ebf2c3f18,0x3e89beb83f62bf6d,0xbf7a3f73bf043edb,0x3ee6bf093f75bf7b,0xbf6a3f5fbeac3e79,0x3f1dbf313f7fbf80,0xbf513f42be163d49,
0x3f35bf35bf803f80,0xbf353f3500000000,0x3f35bf35bf803f80,0xbf353f3500000000,0x3f35bf35bf803f80,0xbf353f3500000000,0x3f35bf35bf803f80,0xbf353f3500000000,
0x3f35bf3580008000,0x3f35bf35bf803f80,0x3f35bf3580008000,0x3f35bf35bf803f80,0x3f35bf3580008000,0x3f35bf35bf803f80,0x3f35bf3580008000,0x3f35bf35bf803f80,
0xbee6bf093f623f55,0x3ecf3efcbf67bf5c,0xbf1dbf313f463f35,0x3f133f27bf4ebf3e,0xbd97be2f3f7f3f7b,0x3cc93dfbbf80bf7d,0xbe89beb83f753f6d,0x3e603ea1bf78bf71,
0x3f653f583ef13f0e,0xbf6abf5fbedbbf04,0x3f4a3f393f223f35,0xbf51bf42bf18bf2c,0x3f7f3f7c3dc93e48,0xbf80bf7ebd49be16,0x3f773f6f3e953ec4,0xbf7abf73be79beac,
0xbf04bf2c3f553f35,0x3edb3f18bf62bf46,0xbe16beac3f7b3f6d,0x3d493e79bf7fbf75,0xbf78bf803e480000,0x3f713f7dbe95bdc9,0xbf4ebf673f0e3ec4,0x3f3e3f5cbf22bef1,
0x3f5c3f3e3f0e3f35,0xbf67bf4ebef1bf22,0x3f7d3f713e483ec4,0xbf80bf78bdc9be95,0x3e793d493f7b3f80,0xbeacbe16bf75bf7f,0x3f183edb3f553f6d,0xbf2cbf04bf46bf62,
0xbe60befc3f753f55,0x3d973eb8bf7dbf67,0xbf39bf653f223ec4,0x3f1d3f51bf3ebf04,0xbf7cbf7e3dc9be48,0x3f733f80be793d49,0xbf6abf42bef1bf35,0x3f773f583eac3f18,
0x3f7a3f5f3e953f0e,0xbf7fbf6fbe16bedb,0x3f313ee63f463f6d,0xbf4abf13bf2cbf5c,0x3e2fbdfb3f7f3f7b,0xbea1bcc9bf78bf80,0xbecfbf273f623f35,0x3e893f09bf71bf4e,
0xbef1bdc9bf6dbf80,0x3f223e953f553f7b,0xbf75bf46bec4bf35,0x3f7f3f623e483f0e,0xbf62bf7f3ec40000,0x3f463f75bf0ebe48,0xbe95bf223f6d3f35,0x3dc93ef1bf7bbf55,
0xbf62bf7f3ec48000,0x3f463f75bf0ebe48,0xbe95bf223f6d3f35,0x3dc93ef1bf7bbf55,0x3ef13dc93f6d3f80,0xbf22be95bf55bf7b,0x3f753f463ec43f35,0xbf7fbf62be48bf0e,
0xbf39bea1bf46bf7b,0x3f5f3f093f183f67,0x3e2f3f1dbf75bf35,0x3d97becf3f803f5c,0xbeb8bf423f623f0e,0x3dfb3f13bf78bf3e,0xbf7abf773dc9bec4,0x3f653f80beac3e16,
0xbf31bf733f223e48,0x3efc3f58bf4ebedb,0xbf7cbf4abe95bf35,0x3f7f3f6a3d493f04,0x3f6f3f273ef13f55,0xbf7ebf51be79bf2c,0x3e60be893f7f3f6d,0xbee63cc9bf71bf7d,
0xbf80bf4ebe48bf35,0x3f783f71bdc93ef1,0xbedbbf5c3f553ec4,0x3e163f2cbf75bf22,0x3f3e3f7dbf0e0000,0xbf04bf673f463e95,0xbeac3e79bf7bbf6d,0x3f183d493f623f7f,
0xbd49bf183f7b3f35,0xbe793eacbf7fbf62,0x3f673f043f0e3f6d,0xbf7dbf3ebe95bf46,0xbf2cbe16bf55bf80,0x3f5c3edb3f223f75,0xbf71bf783e48bec4,0x3f4e3f80bef13dc9,
0xbefcbf6f3f463e48,0x3e2f3f42bf71bf04,0xbf73bf09bef1bf6d,0x3f803f4a3e163f3e,0x3dfb3f39bf75bf0e,0x3e60bee63f803f4e,0x3f7f3f513dc93f35,0xbf6abf773e79bedb,
0x3f5f3eb83f223f7b,0xbf7cbf27beacbf5c,0xbea1bf583f623ec4,0xbcc93f1dbf7dbf2c,0xbf7ebf31be95bf55,0x3f7a3f65bd493f18,0xbd973f13bf7fbf35,0x3ecfbe893f783f67,
0x3f553e483f353f80,0xbf7bbf0ebec4bf6d,0x3f0e3f7bbf350000,0xbe48bf553f6d3ec4,0xbf55be48bf35bf80,0x3f7b3f0e3ec43f6d,0xbf0ebf7b3f350000,0x3e483f55bf6dbec4,
0x3f0e3f7bbf358000,0xbe48bf553f6d3ec4,0xbf55be48bf35bf80,0x3f7b3f0e3ec43f6d,0xbf0ebf7b3f358000,0x3e483f55bf6dbec4,0x3f553e483f353f80,0xbf7bbf0ebec4bf6d,
0x3f5f3f6fbe953f0e,0xbf13bf7f3f2cbe16,0x3ea1bf093f7f3f35,0xbf313dfbbf5cbf71,0xbf1dbf803f22be48,0x3e603f65bf67be79,0xbf273e2fbf62bf6d,0x3f6a3e893f183f80,
0xbefc3eb8bf75bf55,0x3f513d973f3e3f7d,0x3f733f58bdc93f35,0xbf39bf7e3f04beac,0x3f4a3cc93f463f7b,0xbf7abee6bedbbf78,0xbf42bf7c3ef1bec4,0x3ecf3f77bf4ebd49,
0xbedb3f04bf7bbf35,0x3f4ebd493f463f75,0xbf2cbf7d3f0ebec4,0x3e793f71bf62bdc9,0xbeacbf783f550000,0xbe163f3ebf7fbef1,0x3f803f183e483f6d,0xbf5cbf673e95bf22,
0xbf67bf5c3e48bf35,0x3f183f80bf223e95,0x3f3ebe163f553f6d,0xbf78beacbef1bf7f,0x3f713e793f0e3f80,0xbf7dbf2cbdc9bf62,0xbd493f4ebf7bbec4,0x3f04bedb3f753f46,
0xbf39bf733ef1bf0e,0x3e893f7abf5c3d49,0xbe2f3f4abf7fbec4,0x3f27beb83f673f4e,0x3f6a3d973f223f7b,0xbf7ebf13be16bf71,0xbf58bf5f3e95bf35,0x3ee63f80bf3e3e79,
0x3f31bea13f623f55,0xbf77be60bf04bf80,0xbf7cbf1dbdc9bf6d,0x3f423f6fbedb3f18,0x3ecf3f7fbf463e48,0x3dfbbf513f7d3eac,0x3f09befc3f753f35,0xbf65bcc9bf2cbf78,
0xbf7fbe95bec4bf80,0x3f623f46be483f55,0x3f22bef13f6d3f35,0xbf75bdc9bf0ebf7b,0x3dc93f75bf6d0000,0x3ef1bf223f7b3f0e,0xbf46bf623ec4bf35,0x3e953f7fbf553e48,
0xbdc9bf753f6d8000,0xbef13f22bf7bbf0e,0x3f463f62bec43f35,0xbe95bf7f3f55be48,0xbf7fbe95bec4bf80,0x3f623f46be483f55,0x3f22bef13f6d3f35,0xbf75bdc9bf0ebf7b,
0x3e60bf5f3f7f3e48,0xbf423ecfbf5cbf3e,0xbf393ee6bf62bf35,0x3f7e3e2f3edb3f7d,0xbf51bf4a3e95bf55,0x3ea13f80bf4e3eac,0x3eb83f7fbf463ec4,0x3e89bf583f803e79,
0x3f7a3efc3dc93f7b,0xbf27bf6a3f04bf2c,0xbf31bf653ef1bf35,0x3dfb3f7cbf673e16,0x3f13bf1d3f753f0e,0xbf733cc9bf18bf71,0xbf6f3d97bf22bf6d,0x3f773f093d493f78,
0x3f183f67bf0e3f35,0x3d49bf783f75bdc9,0xbf5cbf2c3e48bf6d,0x3eac3f7dbf463ef1,0xbe163f71bf7b0000,0x3f3ebf043f623f22,0xbe79bf803f55bec4,0xbedb3f4ebf7fbe95,
0xbf4e3edbbf55bf35,0x3f803e793e953f7f,0x3f04bf3e3f7b3ec4,0xbf713e16bf22bf62,0xbf7dbeacbe48bf80,0x3f2c3f5cbef13f46,0x3f78bd493f0e3f6d,0xbf67bf183dc9bf75,
0xbf65bf093dc9bf7b,0x3eb83f77bf3e3f18,0x3f4a3f31be953f6d,0xbe2fbf7f3f5cbedb,0xbf27bf513ef1bf55,0xbcc93f7ebf713e79,0x3efc3f6abf223f35,0x3e60bf733f7dbd49,
0x3ee6bf583f7f3e48,0xbf6f3e89bf2cbf4e,0xbf1d3f39bf75bec4,0x3f7cbd973f043f67,0x3f42bf133f623f0e,0xbf80bdfbbeacbf78,0xbf5f3ecfbf46bf35,0x3f7a3ea13e163f80,
0x3f6d3ec400003f80,0xbec4bf6d3f35bf35,0xbf6dbec40000bf80,0x3ec43f6dbf353f35,0x3f6d3ec400003f80,0xbec4bf6d3f35bf35,0xbf6dbec40000bf80,0x3ec43f6dbf353f35,
0xbec43f6dbf808000,0x3f6dbec43f353f35,0x3ec4bf6d3f808000,0xbf6d3ec4bf35bf35,0xbec43f6dbf808000,0x3f6dbec43f353f35,0x3ec4bf6d3f808000,0xbf6d3ec4bf35bf35,
0xbf7f3e2fbef1bf55,0x3f393f1dbeac3f78,0x3f77beb83f223f35,0xbf58bee63e16bf80,0xbf73be60bdc9bf7b,0x3ecf3f5fbf2c3f4e,0x3f7e3cc93e953f6d,0xbf13bf423f04bf67,
0xbd97bf7c3f62bf0e,0xbf313f4abf71be79,0x3e893f6fbf463f35,0x3f09bf653f7d3d49,0x3ea1bf7a3f7fbe48,0xbf6a3efcbf3ebf18,0xbdfb3f80bf753ec4,0x3f51bf273f5c3edb,
0x3f7dbeac3f0e3f35,0xbf3ebf043e95bf7f,0xbf78bd49be48bf6d,0x3edb3f4ebf223f62,0x3f18bf673f7b0000,0xbf803e79bef1bf46,0xbf5c3f2cbf55bec4,0x3f713e163dc93f75,
0x3e163f71bf553f35,0x3f2cbf5c3f753dc9,0x3e79bf803f7bbec4,0xbf673f18bf46bef1,0x3f4e3edbbe483f80,0xbd49bf783f62bf22,0xbf04bf3e3f0ebf6d,0xbeac3f7dbf7f3e95,
0xbf7c3dfbbe95bf55,0x3ee63f39bf183f71,0x3f6abf273f463ec4,0xbf5fbe603d49bf78,0xbf093f77bf7f3e48,0x3f7fbeb83f043f2c,0xbcc9bf733f62bf35,0xbf4a3f51bf67be16,
0x3e2fbf7e3f75bf0e,0xbf653f31bf4ebeac,0x3ecf3f42bf223f6d,0x3efcbf7a3f80be79,0xbf58be893dc9bf7b,0x3d973f6fbf5c3f3e,0x3f80bea13ef13f35,0xbf1dbf133edbbf7d,
0xbf22bef13ec4bf80,0xbe953f7fbf7b3f0e,0xbdc93f75bf6d3f35,0x3f62bf463f553e48,0x3f46bf623f6d0000,0xbf753dc9be48bf55,0xbf7f3e95bec4bf35,0x3ef13f22bf0e3f7b,
0x3f46bf623f6d8000,0xbf753dc9be48bf55,0xbf7f3e95bec4bf35,0x3ef13f22bf0e3f7b,0x3f223ef1bec43f80,0x3e95bf7f3f7bbf0e,0x3dc9bf753f6dbf35,0xbf623f46bf55be48,
0x3eb83f27bf223f7b,0x3f1dbf7c3f7dbeac,0xbf7a3e89be95bf35,0x3ea13f31bf2c3f78,0xbf803ee6bef1bf0e,0x3efc3f09bf043f80,0x3f13bf7e3f7fbec4,0xbf7f3ecfbedbbf18,
0xbf6f3f42bf46be48,0x3f4a3e2fbe163f71,0x3e60bf773f75bf35,0xbf733f39bf3ebe79,0x3cc9bf653f62bf55,0xbf5f3f58bf5cbd49,0x3f513dfbbdc93f6d,0x3d97bf6a3f67bf4e,
0x3eacbf783f7bbf35,0xbf7d3f2cbf22be95,0xbf803f18bf0ebec4,0x3f043edbbef13f7f,0xbf673f5cbf550000,0x3f4e3d49bdc93f62,0x3f3e3e16be483f6d,0x3e79bf713f75bf46,
0x3f71be793e483f35,0xbe16bf3e3f46bf75,0xbd49bf4e3f55bf6d,0xbf5c3f67bf623dc9,0xbedbbf043f0ebf80,0xbf183f80bf7f3ef1,0xbf2c3f7dbf7b3ec4,0x3f78beac3e953f22,
0xbf7e3f39bf22be48,0x3f093ea1bedb3f78,0x3d97bf513f62bf6d,0xbf6f3f5fbf4e3d49,0x3f77becf3e953f0e,0xbe2fbf273f3ebf7d,0xbee63f7abf7f3f35,0x3f80bf1d3f043eac,
0xbdfbbf313f46bf7b,0xbf583f73bf673e79,0x3f7fbf133ef13ec4,0xbeb8befc3f18bf80,0xbe893f6abf753f55,0x3f7cbf423f2c3e16,0xbf653e60bdc9bf35,0xbcc93f4abf5c3f71,
0x3e483f0ebf353f80,0x3f55bf7b3f6dbec4,0x3f7bbf553f350000,0xbf0ebe483ec4bf6d,0xbe48bf0e3f35bf80,0xbf553f7bbf6d3ec4,0xbf7b3f55bf350000,0x3f0e3e48bec43f6d,
0xbf7b3f55bf358000,0x3f0e3e48bec43f6d,0x3e483f0ebf353f80,0x3f55bf7b3f6dbec4,0x3f7bbf553f358000,0xbf0ebe483ec4bf6d,0xbe48bf0e3f35bf80,0xbf553f7bbf6d3ec4,
0x3f4abf803f75bf0e,0xbf583ea1bd49bf18,0x3f42be2fbdc93f35,0x3eb8bf5f3f78bf67,0xbf773f6abf463e48,0x3f133d97beac3f5c,0xbee6be603ef1bf6d,0xbf313f7ebf7d3f2c,
0x3f1d3cc9be953f55,0x3f09bf733f80bf4e,0xbf273f7cbf7f3f35,0x3f6fbefc3e793edb,0xbe89becf3f22bf7b,0xbf513f7fbf713f04,0x3f65bf7a3f62bec4,0xbf393dfb3e16bf3e,
0xbf2c3e163e48bf35,0xbf043f67bf7f3f62,0xbf713f78bf553ec4,0x3f18bd49be953f46,0x3f80bf4e3f0e0000,0xbe79beac3f22bf75,0x3edbbf5c3f7bbf6d,0xbf7d3f3ebef1bdc9,
0x3f3ebf7d3f7bbf35,0xbf5c3edbbdc9bef1,0xbeacbe793f0ebf6d,0xbf4e3f80bf753f22,0xbd493f18bf553f80,0x3f78bf713f46be95,0x3f67bf043e483ec4,0x3e16bf2c3f62bf7f,
0xbf6a3f7fbf623f0e,0x3f1dbe2fbe793f2c,0xbf583efcbdc9bec4,0xbea13f39bf713f7d,0xbcc9bee63f46bf7b,0xbf773f7abf4e3edb,0x3f51bf7e3f75bf35,0xbf423eb83d49bf04,
0xbecfbd973ef1bf55,0xbf4a3f7cbf783f3e,0x3f09bf5f3f7fbf6d,0xbf733f31beacbe16,0x3f80bf653f22be48,0xbe89be603f18bf67,0x3f13bdfbbe953f35,0x3f27bf6f3f80bf5c,
0x3e95bf223f6dbf80,0xbf7f3f62bf0e3e48,0xbef13dc93ec4bf35,0xbf463f75bf7b3f55,0xbf753f46bec40000,0xbdc93ef1bf553f7b,0xbf623f7fbf6d3f35,0x3f22be95be483f0e,
0x3f75bf463ec48000,0x3dc9bef13f55bf7b,0x3f62bf7f3f6dbf35,0xbf223e953e48bf0e,0x3e95bf223f6dbf80,0xbf7f3f62bf0e3e48,0xbef13dc93ec4bf35,0xbf463f75bf7b3f55,
0xbf513f1dbdc9be48,0xbee63f31bf783f80,0xbeb83d973ef1bf35,0xbf5f3f7abf713f4e,0xbf583f77bf753f55,0x3f27becfbe163edb,0xbf803f73bf223ec4,0x3dfb3e2fbf2c3f5c,
0x3f13bf4a3f7fbf7b,0xbf653f39be79bd49,0x3f6fbf7f3f62bf35,0xbefc3e603eacbf18,0xbf093e893e95bf0e,0xbf423f6abf7d3f67,0x3cc9bea13f46bf6d,0xbf7e3f7cbf3e3f04,
0xbf783f80bf553f35,0x3eacbe16bef13f22,0xbf4e3f67bf7b3f6d,0x3f2cbf04bdc93e95,0xbf5c3f3ebe480000,0xbedb3f18bf753f7f,0xbf7d3f71bf0e3ec4,0xbd493e79bf463f62,
0xbe793d493f0ebf35,0xbf713f7dbf623f46,0xbf183edb3e48bec4,0xbf3e3f5cbf7f3f75,0x3f04bf2c3f7bbf80,0xbf673f4ebe953dc9,0x3e16beac3f55bf6d,0xbf803f78bf223ef1,
0xbf423f51bf7f3f7b,0x3f31bf1dbd493e16,0xbf5f3f6abf753f6d,0x3f09bee6be793eac,0xbf733f7abf623f55,0x3eb8be89bedb3f04,0xbf7e3f80bf463f35,0x3e2fbd97bf183f2c,
0xbf273f133dc9be48,0xbf393f4abf803f7d,0xbefc3ecf3e95bec4,0xbf583f65bf783f71,0xbea13e603ef1bf0e,0xbf6f3f77bf673f5c,0xbdfb3cc93f22bf35,0xbf7c3f7fbf4e3f3e,
};
__device__ __align__(1024) uint8_t g_hT[32 * 262144];
__device__ __align__(1024) bf16 g_U[128 * 2 * 8 * 1024];
__device__ __align__(16) uint2 g_gate[2048];
__device__ __align__(16) uint4 g_agg[8 * 1024];
__device__ unsigned g_cnt[8 * 32];
constexpr int CNT_U = 0, CNT_V = 1, CNT_H = 2  , CNT_DONE = 4, CNT_EPOCH = 5;
#define PROFK(i) do { } while (0)
#define PROFC(i) do { } while (0)
#define PROF(i) do { } while (0)
#define PROFG(i) do { } while (0)
#define PROFS(i) do { } while (0)

constexpr int STAGE_BYTES = 49152;
constexpr int OFF_W = 0;
constexpr int OFF_F = 36864;
constexpr int OFF_TW = 45056;
constexpr int OFF_HS = 49152;
constexpr int OFF_A2 = 32768, OFF_B2 = 114688;
constexpr int OFF_U = 4 * STAGE_BYTES;
constexpr int OFF_G = OFF_U + 32768;
constexpr int OFF_BAR = OFF_G + 1024;
constexpr int OFF_REL = OFF_BAR + 272;
constexpr int OFF_GS = OFF_BAR + 304;
constexpr int OFF_DUMMY = OFF_GS + 128;
constexpr int SMEM_BYTES = OFF_DUMMY + 16;
constexpr int BAR_FULL = 0  , BAR_FULL2 = 4  , BAR_X = 9, BAR_U = 10, BAR_W = 11, BAR_H1 = 12, BAR_V = 13,
              BAR_G1 = 14, BAR_HF = 15,
              BAR_H = 16  ,
              BAR_CD = 26, BAR_EMPTY2 = 27  ,
              BAR_C = 32, NBAR = 33;

#define DEVI __device__ __forceinline__
constexpr unsigned SPIN_LIMIT = 1u << 22;

DEVI uint32_t smem_u32(const void* p) { return (uint32_t)__cvta_generic_to_shared(p); }
DEVI uint64_t gtime() { uint64_t t; asm volatile("mov.u64 %0, %%globaltimer;" : "=l"(t)); return t; }
DEVI void mbar_init(uint32_t bar, uint32_t cnt) { asm volatile("mbarrier.init.shared::cta.b64 [%0], %1;" :: "r"(bar), "r"(cnt) : "memory"); }
DEVI void mbar_expect_tx(uint32_t bar, uint32_t bytes) { asm volatile("mbarrier.arrive.expect_tx.shared::cta.b64 _, [%0], %1;" :: "r"(bar), "r"(bytes) : "memory"); }
DEVI void mbar_arrive(uint32_t bar) { asm volatile("mbarrier.arrive.shared::cta.b64 _, [%0];" :: "r"(bar) : "memory"); }
DEVI void mbar_wait(uint32_t bar, uint32_t parity) {
    asm volatile("{\n.reg .pred p;\n.reg .u32 n;\nmov.u32 n, 0;\n"
                 "LW:\nmbarrier.try_wait.parity.shared::cta.b64 p, [%0], %1;\n@p bra LD;\n"
                 "add.u32 n, n, 1;\nsetp.lt.u32 p, n, %2;\n@p bra LW;\nLD:\n}"
                 :: "r"(bar), "r"(parity), "n"(1 << 17) : "memory");
}
DEVI bool elect() {
    uint32_t p;
    asm volatile("{\n.reg .pred P;\nelect.sync _|P, 0xffffffff;\nselp.u32 %0, 1, 0, P;\n}" : "=r"(p));
    return p;
}
DEVI void fence_barrier_init() { asm volatile("fence.mbarrier_init.release.cluster;" ::: "memory"); }
DEVI void fence_proxy_async_smem() { asm volatile("fence.proxy.async.shared::cta;" ::: "memory"); }
DEVI void helper_sync() { asm volatile("bar.sync 1, 128;" ::: "memory"); }

DEVI void wait_counter(const unsigned* p, unsigned target) {
    for (unsigned n = 0;; n++) {
        unsigned v;
        asm volatile("ld.relaxed.gpu.global.u32 %0, [%1];" : "=r"(v) : "l"(p) : "memory");
        if ((int)(v - target) >= 0 || n > SPIN_LIMIT) break;
    }
}
DEVI void signal_counter(unsigned* p) {
    asm volatile("red.relaxed.gpu.global.add.u32 [%0], 1;" :: "l"(p) : "memory");
}

DEVI void tma_load_3d(uint32_t dst, const CUtensorMap* map, uint32_t bar, int c0, int c1, int c2) {
    asm volatile("cp.async.bulk.tensor.3d.shared::cluster.global.mbarrier::complete_tx::bytes [%0], [%1, {%3, %4, %5}], [%2];"
        :: "r"(dst), "l"(map), "r"(bar), "r"(c0), "r"(c1), "r"(c2) : "memory");
}
DEVI void tma_load_4d(uint32_t dst, const CUtensorMap* map, uint32_t bar, int c0, int c1, int c2, int c3) {
    asm volatile("cp.async.bulk.tensor.4d.shared::cluster.global.mbarrier::complete_tx::bytes [%0], [%1, {%3, %4, %5, %6}], [%2];"
        :: "r"(dst), "l"(map), "r"(bar), "r"(c0), "r"(c1), "r"(c2), "r"(c3) : "memory");
}
DEVI void tma_store_5d(const CUtensorMap* map, uint32_t src, int c0, int c4) {
    asm volatile("cp.async.bulk.tensor.5d.global.shared::cta.bulk_group [%0, {%2, %4, %4, %4, %3}], [%1];"
        :: "l"(map), "r"(src), "r"(c0), "r"(c4), "r"(0) : "memory");
}
DEVI void tma_store_4d(const CUtensorMap* map, uint32_t src, int c0, int c1, int c2, int c3) {
    asm volatile("cp.async.bulk.tensor.4d.global.shared::cta.bulk_group [%0, {%2, %3, %4, %5}], [%1];"
        :: "l"(map), "r"(src), "r"(c0), "r"(c1), "r"(c2), "r"(c3) : "memory");
}
DEVI void bulk_load(uint32_t dst, const void* src, uint32_t bytes, uint32_t bar) {
    asm volatile("cp.async.bulk.shared::cluster.global.mbarrier::complete_tx::bytes [%0], [%1], %2, [%3];"
        :: "r"(dst), "l"(src), "r"(bytes), "r"(bar) : "memory");
}
DEVI void bulk_prefetch_l2(const void* src, uint32_t bytes) {
    asm volatile("cp.async.bulk.prefetch.L2.global [%0], %1;" :: "l"(src), "r"(bytes) : "memory");
}
DEVI void tma_store_3d(const CUtensorMap* map, uint32_t src, int c0, int c1, int c2) {
    asm volatile("cp.async.bulk.tensor.3d.global.shared::cta.bulk_group [%0, {%2, %3, %4}], [%1];"
        :: "l"(map), "r"(src), "r"(c0), "r"(c1), "r"(c2) : "memory");
}
DEVI void pause(unsigned n) {
    asm volatile("{\n.reg .pred p;\n.reg .u32 a, b;\nmov.u32 a, %%clock;\n"
                 "LP:\nmov.u32 b, %%clock;\nsub.u32 b, b, a;\nsetp.lt.u32 p, b, %0;\n@p bra LP;\n}" :: "r"(n) : "memory");
}
DEVI void bulk_store(void* dst, uint32_t src, uint32_t bytes) {
    asm volatile("cp.async.bulk.global.shared::cta.bulk_group [%0], [%1], %2;" :: "l"(dst), "r"(src), "r"(bytes) : "memory");
}
DEVI void bulk_commit() { asm volatile("cp.async.bulk.commit_group;" ::: "memory"); }
DEVI void bulk_wait0() { asm volatile("cp.async.bulk.wait_group 0;" ::: "memory"); }

DEVI void wgmma_fence() { asm volatile("wgmma.fence.sync.aligned;" ::: "memory"); }
DEVI void wgmma_commit() { asm volatile("wgmma.commit_group.sync.aligned;" ::: "memory"); }
template<int N> DEVI void wgmma_wait() { asm volatile("wgmma.wait_group.sync.aligned %0;" :: "n"(N) : "memory"); }
template<int N> DEVI void wgmma_wait_all(float (&d)[N]) {
    wgmma_wait<0>();
#pragma unroll
    for (int i = 0; i < N; i++) asm volatile("" : "+f"(d[i]) :: "memory");
}
template<int R> DEVI void reg_alloc() { asm volatile("setmaxnreg.inc.sync.aligned.u32 %0;" :: "n"(R)); }
template<int R> DEVI void reg_dealloc() { asm volatile("setmaxnreg.dec.sync.aligned.u32 %0;" :: "n"(R)); }

DEVI uint64_t make_desc(uint32_t addr, uint32_t lbo, uint32_t sbo, uint32_t mode = 1) {
    return (uint64_t)(((addr & 0x3FFFF) >> 4) | ((lbo >> 4) << 16)) | ((uint64_t)((sbo >> 4) | (mode << 30)) << 32);
}

#define ACC8(a, o) "+f"(a[o+0]), "+f"(a[o+1]), "+f"(a[o+2]), "+f"(a[o+3]), "+f"(a[o+4]), "+f"(a[o+5]), "+f"(a[o+6]), "+f"(a[o+7])
#define ACC32(a, o) ACC8(a, o), ACC8(a, o+8), ACC8(a, o+16), ACC8(a, o+24)

DEVI void wgmma_n256(float (&d)[128], uint64_t da, uint64_t db, int scale_d) {
    asm volatile("{\n.reg .pred p;\nsetp.ne.b32 p, %130, 0;\n"
        "wgmma.mma_async.sync.aligned.m64n256k16.f32.bf16.bf16 "
        "{%0, %1, %2, %3, %4, %5, %6, %7, %8, %9, %10, %11, %12, %13, %14, %15, "
        "%16, %17, %18, %19, %20, %21, %22, %23, %24, %25, %26, %27, %28, %29, %30, %31, "
        "%32, %33, %34, %35, %36, %37, %38, %39, %40, %41, %42, %43, %44, %45, %46, %47, "
        "%48, %49, %50, %51, %52, %53, %54, %55, %56, %57, %58, %59, %60, %61, %62, %63, "
        "%64, %65, %66, %67, %68, %69, %70, %71, %72, %73, %74, %75, %76, %77, %78, %79, "
        "%80, %81, %82, %83, %84, %85, %86, %87, %88, %89, %90, %91, %92, %93, %94, %95, "
        "%96, %97, %98, %99, %100, %101, %102, %103, %104, %105, %106, %107, %108, %109, %110, %111, "
        "%112, %113, %114, %115, %116, %117, %118, %119, %120, %121, %122, %123, %124, %125, %126, %127}, "
        "%128, %129, p, 1, 1, 0, 0;\n}\n"
        : ACC32(d, 0), ACC32(d, 32), ACC32(d, 64), ACC32(d, 96)
        : "l"(da), "l"(db), "r"(scale_d));
}
template<int TB>
DEVI void wgmma_n128(float (&d)[64], uint64_t da, uint64_t db, int scale_d) {
    asm volatile("{\n.reg .pred p;\nsetp.ne.b32 p, %66, 0;\n"
        "wgmma.mma_async.sync.aligned.m64n128k16.f32.bf16.bf16 "
        "{%0, %1, %2, %3, %4, %5, %6, %7, %8, %9, %10, %11, %12, %13, %14, %15, "
        "%16, %17, %18, %19, %20, %21, %22, %23, %24, %25, %26, %27, %28, %29, %30, %31, "
        "%32, %33, %34, %35, %36, %37, %38, %39, %40, %41, %42, %43, %44, %45, %46, %47, "
        "%48, %49, %50, %51, %52, %53, %54, %55, %56, %57, %58, %59, %60, %61, %62, %63}, "
        "%64, %65, p, 1, 1, 1, %67;\n}\n"
        : ACC32(d, 0), ACC32(d, 32)
        : "l"(da), "l"(db), "r"(scale_d), "n"(TB));
}
template<int SCALE_D>
DEVI void wgmma_rs_n128(float (&d)[64], const uint4& a, uint64_t db) {
    asm volatile("{\n.reg .pred p;\nsetp.ne.b32 p, %69, 0;\n"
        "wgmma.mma_async.sync.aligned.m64n128k16.f32.bf16.bf16 "
        "{%0, %1, %2, %3, %4, %5, %6, %7, %8, %9, %10, %11, %12, %13, %14, %15, "
        "%16, %17, %18, %19, %20, %21, %22, %23, %24, %25, %26, %27, %28, %29, %30, %31, "
        "%32, %33, %34, %35, %36, %37, %38, %39, %40, %41, %42, %43, %44, %45, %46, %47, "
        "%48, %49, %50, %51, %52, %53, %54, %55, %56, %57, %58, %59, %60, %61, %62, %63}, "
        "{%64, %65, %66, %67}, %68, p, 1, 1, 1;\n}\n"
        : ACC32(d, 0), ACC32(d, 32)
        : "r"(a.x), "r"(a.y), "r"(a.z), "r"(a.w), "l"(db), "n"(SCALE_D));
}
DEVI void wgmma_n16(float (&d)[8], uint64_t da, uint64_t db) {
    asm volatile("{\n.reg .pred p;\nsetp.ne.b32 p, 0, 0;\n"
        "wgmma.mma_async.sync.aligned.m64n16k16.f32.bf16.bf16 "
        "{%0, %1, %2, %3, %4, %5, %6, %7}, %8, %9, p, 1, 1, 1, 0;\n}\n"
        : ACC8(d, 0)
        : "l"(da), "l"(db));
}
template<int SCALE_D>
DEVI void wgmma_rs_n64(float (&d)[32], const uint32_t (&a)[4], uint64_t db) {
    asm volatile("{\n.reg .pred p;\nsetp.ne.b32 p, %37, 0;\n"
        "wgmma.mma_async.sync.aligned.m64n64k16.f32.bf16.bf16 "
        "{%0, %1, %2, %3, %4, %5, %6, %7, %8, %9, %10, %11, %12, %13, %14, %15, "
        "%16, %17, %18, %19, %20, %21, %22, %23, %24, %25, %26, %27, %28, %29, %30, %31}, "
        "{%32, %33, %34, %35}, %36, p, 1, 1, 0;\n}\n"
        : ACC32(d, 0)
        : "r"(a[0]), "r"(a[1]), "r"(a[2]), "r"(a[3]), "l"(db), "n"(SCALE_D));
}
DEVI void ldsm_x4_t(uint32_t (&r)[4], uint32_t addr) {
    asm volatile("ldmatrix.sync.aligned.m8n8.x4.trans.shared.b16 {%0, %1, %2, %3}, [%4];"
        : "=r"(r[0]), "=r"(r[1]), "=r"(r[2]), "=r"(r[3]) : "r"(addr) : "memory");
}
DEVI void ldsm_x4(uint32_t (&r)[4], uint32_t addr) {
    asm volatile("ldmatrix.sync.aligned.m8n8.x4.shared.b16 {%0, %1, %2, %3}, [%4];"
        : "=r"(r[0]), "=r"(r[1]), "=r"(r[2]), "=r"(r[3]) : "r"(addr) : "memory");
}
DEVI void stsm_x4(uint32_t addr, uint32_t r0, uint32_t r1, uint32_t r2, uint32_t r3) {
    asm volatile("stmatrix.sync.aligned.m8n8.x4.shared.b16 [%0], {%1, %2, %3, %4};"
        :: "r"(addr), "r"(r0), "r"(r1), "r"(r2), "r"(r3) : "memory");
}
DEVI void stsm_x4_t(uint32_t addr, uint32_t r0, uint32_t r1, uint32_t r2, uint32_t r3) {
    asm volatile("stmatrix.sync.aligned.m8n8.x4.trans.shared.b16 [%0], {%1, %2, %3, %4};"
        :: "r"(addr), "r"(r0), "r"(r1), "r"(r2), "r"(r3) : "memory");
}
DEVI uint32_t movm(uint32_t a) { uint32_t d; asm volatile("movmatrix.sync.aligned.m8n8.trans.b16 %0, %1;" : "=r"(d) : "r"(a)); return d; }
DEVI uint32_t pack2(float lo, float hi) { uint32_t d; asm("cvt.rn.bf16x2.f32 %0, %1, %2;" : "=r"(d) : "f"(hi), "f"(lo)); return d; }
DEVI float bf_lo(uint32_t v) { return __uint_as_float(v << 16); }
DEVI float bf_hi(uint32_t v) { return __uint_as_float(v & 0xffff0000u); }
DEVI float bf_round(float v) { return __bfloat162float(__float2bfloat16_rn(v)); }
DEVI uint32_t bf_mul2(uint32_t a, uint32_t b) { uint32_t d; asm("mul.rn.bf16x2 %0, %1, %2;" : "=r"(d) : "r"(a), "r"(b)); return d; }
DEVI uint4 lds128u(uint32_t a) { uint4 v; asm volatile("ld.shared.v4.u32 {%0, %1, %2, %3}, [%4];" : "=r"(v.x), "=r"(v.y), "=r"(v.z), "=r"(v.w) : "r"(a) : "memory"); return v; }
DEVI void sts128u(uint32_t a, uint32_t x, uint32_t y, uint32_t z, uint32_t w) { asm volatile("st.shared.v4.u32 [%0], {%1, %2, %3, %4};" :: "r"(a), "r"(x), "r"(y), "r"(z), "r"(w) : "memory"); }
DEVI uint2 lds64u(uint32_t a) { uint2 v; asm volatile("ld.shared.v2.u32 {%0, %1}, [%2];" : "=r"(v.x), "=r"(v.y) : "r"(a) : "memory"); return v; }
DEVI uint32_t ldg32u(const void* p) { uint32_t v; asm volatile("ld.global.nc.u32 %0, [%1];" : "=r"(v) : "l"(p) : "memory"); return v; }
DEVI void sts64(uint32_t a, float x, float y) { asm volatile("st.shared.v2.f32 [%0], {%1, %2};" :: "r"(a), "f"(x), "f"(y) : "memory"); }
DEVI void sts32(uint32_t a, uint32_t v) { asm volatile("st.shared.u32 [%0], %1;" :: "r"(a), "r"(v) : "memory"); }
DEVI uint32_t lds16(uint32_t a) { uint32_t v; asm volatile("ld.shared.u16 %0, [%1];" : "=r"(v) : "r"(a) : "memory"); return v; }
DEVI void cmul2(uint32_t& x, uint32_t& y, uint32_t c, uint32_t s) {
    asm("{\n.reg .b32 t, u;\nxor.b32 t, %3, 0x80008000;\nmul.rn.bf16x2 t, %1, t;\nmul.rn.bf16x2 u, %1, %2;\n"
        "fma.rn.bf16x2 %1, %0, %3, u;\nfma.rn.bf16x2 %0, %0, %2, t;\n}" : "+r"(x), "+r"(y) : "r"(c), "r"(s));
}
DEVI void sts16(uint32_t a, float v) { asm volatile("st.shared.u16 [%0], %1;" :: "r"(a), "r"(pack2(v, v)) : "memory"); }

DEVI float2 cmul(float2 a, float2 b) { return make_float2(fmaf(a.x, b.x, -a.y * b.y), fmaf(a.x, b.y, a.y * b.x)); }
DEVI float2 cfma(float2 a, float2 b, float2 c) { return make_float2(fmaf(a.x, b.x, fmaf(-a.y, b.y, c.x)), fmaf(a.x, b.y, fmaf(a.y, b.x, c.y))); }
DEVI float2 cadd(float2 a, float2 b) { return make_float2(a.x + b.x, a.y + b.y); }
DEVI float2 csub(float2 a, float2 b) { return make_float2(a.x - b.x, a.y - b.y); }
DEVI void fft4(float2& a, float2& b, float2& c, float2& d) {
    const float2 s0 = cadd(a, c), s1 = csub(a, c), s2 = cadd(b, d), t = csub(b, d), s3 = make_float2(t.y, -t.x);
    a = cadd(s0, s2); b = cadd(s1, s3); c = csub(s0, s2); d = csub(s1, s3);
}

struct Params {
    const bf16 *lam_re, *lam_im, *log_dt, *dskip, *gate_w, *c_re, *c_im, *w_r, *w_i;
    int swapB;
    uint8_t perm[68];
};

DEVI void pace(uint32_t cnt_addr) {
    uint32_t v0, v;
    asm volatile("ld.volatile.shared.u32 %0, [%1];" : "=r"(v0) : "r"(cnt_addr) : "memory");
    const unsigned t0 = clock();
    do {
        __nanosleep(20);
        asm volatile("ld.volatile.shared.u32 %0, [%1];" : "=r"(v) : "r"(cnt_addr) : "memory");
    } while (v == v0 && (unsigned)clock() - t0 < 1300u);
}

DEVI void radix8(uint32_t sb, uint32_t gtab, int hf, int w, int lane, int bar) {
    const uint64_t dg = make_desc(gtab, 128, 256, 0);
    const uint32_t st = sb + OFF_U + hf * 8192 + (lane >> 4) * 16384 + (lane & 7) * 128 + (((2 * w + ((lane >> 3) & 1)) ^ (lane & 7)) << 4);
    float acc[8][8];
    const uint64_t da = make_desc(sb + OFF_U + hf * 8192, 16, 16384);
    wgmma_fence();
#pragma unroll
    for (int i = 0; i < 8; i++) wgmma_n16(acc[i], da + 64 * i, dg);
    wgmma_commit();
    wgmma_wait<0>();
    asm volatile("bar.sync %0, 128;" :: "r"(bar) : "memory");
#pragma unroll
    for (int i = 0; i < 8; i++)
        stsm_x4_t((st ^ ((i & 3) << 4)) + i * 1024,
                  pack2(acc[i][0], acc[i][1]), pack2(acc[i][2], acc[i][3]), pack2(acc[i][4], acc[i][5]), pack2(acc[i][6], acc[i][7]));
}

template<int N> DEVI void c_take(float (&acc)[32], uint32_t (&p)[16]) {
    wgmma_wait<N>();
#pragma unroll
    for (int i = 0; i < 32; i++) asm volatile("" : "+f"(acc[i]) :: "memory");
#pragma unroll
    for (int i = 0; i < 16; i++) p[i] = pack2(acc[2 * i], acc[2 * i + 1]);
}
DEVI void c_mm4(float (&acc)[32], const uint32_t (&a)[4][4], uint64_t df) {
    wgmma_rs_n64<0>(acc, a[0], df);
    wgmma_rs_n64<1>(acc, a[1], df + 2);
    wgmma_rs_n64<1>(acc, a[2], df + 4);
    wgmma_rs_n64<1>(acc, a[3], df + 6);
    wgmma_commit();
}
template<int H> DEVI void c_mm2(float (&acc)[2][32], const uint32_t (&a)[2][2][4], uint64_t df) {
    wgmma_fence();
#pragma unroll
    for (int i = 0; i < 2; i++) {
        wgmma_rs_n64<H>(acc[i], a[i][0], df + 2 * H);
        wgmma_rs_n64<1>(acc[i], a[i][1], df + 2 * H + 4);
        wgmma_commit();
    }
}
DEVI void c_twiddle(uint32_t (&p)[16], uint32_t (&a)[2][2][4], const uint4* tw) {
#pragma unroll
    for (int jp = 0; jp < 2; jp++)
#pragma unroll
        for (int hh = 0; hh < 2; hh++) {
            const uint4 w = tw[hh * 2 + jp];
#pragma unroll
            for (int jl = 0; jl < 2; jl++) {
                const int o = 4 * jp + 2 * jl + hh;
                cmul2(p[o], p[8 + o], jl ? w.z : w.x, jl ? w.w : w.y);
                a[jp][0][2 * hh + jl] = movm(p[o]);
                a[jp][1][2 * hh + jl] = movm(p[8 + o]);
            }
        }
}
template<bool LW> DEVI void c_stage(float (&acc)[2][32], const uint4 (&tw)[8], uint64_t df, uint32_t (&w)[2][4][4], uint32_t wa, uint32_t wm) {
    uint32_t p[16], a0[2][2][4], a1[2][2][4];
    c_take<1>(acc[0], p);
    c_twiddle(p, a0, tw);
    c_take<0>(acc[1], p);
    if (LW) {
#pragma unroll
        for (int j = 0; j < 4; j++) ldsm_x4_t(w[0][j], (j < 2 ? wa : wm) + (j & 1) * 512);
    }
    c_mm2<0>(acc, a0, df);
    c_twiddle(p, a1, tw + 4);
    if (LW) {
#pragma unroll
        for (int j = 0; j < 4; j++) ldsm_x4_t(w[1][j], ((j < 2 ? wa : wm) ^ 32) + (j & 1) * 512);
    }
    c_mm2<1>(acc, a1, df);
}

DEVI void phase_c(uint32_t sb, int mrow, int warp, int lane) {
    PROFC(0);
    const uint64_t df = make_desc(sb + OFF_F, 16, 1024);
    float acc[2][32];
    uint4 tw[8];
    uint32_t w[2][4][4];
    const uint32_t xa = sb + OFF_U + ((lane >> 4) * 4 + ((lane & 7) >> 1)) * 1024 + warp * 128
                      + ((((lane & 1) * 4 + ((lane >> 3) & 1)) ^ warp ^ ((lane >> 1) & 3)) << 4);
    const uint32_t wo = sb + OFF_W + (lane >> 4) * 18432 + (lane & 7) * 64 + ((((lane >> 3) & 1) ^ ((lane >> 1) & 3)) << 4);
    const uint32_t wa = wo + warp * 1152, wm = wo + 9216 + mrow * 1152;
    {
        uint32_t a[2][4][4];
#pragma unroll
        for (int h = 0; h < 2; h++)
#pragma unroll
            for (int s = 0; s < 4; s++) ldsm_x4_t(a[h][s], (xa ^ (h * 32)) + (s & 1) * 8192 + (s >> 1) * 16384);
#pragma unroll
        for (int i = 0; i < 8; i++) tw[i] = lds128u(sb + OFF_TW + lane * 16 + i * 512);
        wgmma_fence();
        c_mm4(acc[0], a[0], df);
        c_mm4(acc[1], a[1], df);
    }
    PROFC(1);
    c_stage<true>(acc, tw, df, w, wa, wm);
    PROFC(2);
#pragma unroll
    for (int h = 0; h < 2; h++) {
        uint32_t p[16], a[4][4];
        c_take<1>(acc[h], p);
#pragma unroll
        for (int j = 0; j < 4; j++)
#pragma unroll
            for (int hh = 0; hh < 2; hh++) {
                cmul2(p[2 * j + hh], p[8 + 2 * j + hh], w[h][j][hh], w[h][j][2 + hh]);
                a[j >> 1][2 * (j & 1) + hh] = p[8 + 2 * j + hh];
                a[2 + (j >> 1)][2 * (j & 1) + hh] = p[2 * j + hh];
            }
        wgmma_fence();
        c_mm4(acc[h], a, df);
    }
    PROFC(3);
    c_stage<false>(acc, tw, df, w, wa, wm);
    PROFC(4);
#pragma unroll
    for (int h = 0; h < 2; h++) {
        uint32_t p[16];
        if (h) c_take<0>(acc[1], p); else c_take<1>(acc[0], p);
#pragma unroll
        for (int s = 0; s < 4; s++)
            stsm_x4_t((xa ^ (h * 32)) + (s & 1) * 8192 + ((s >> 1) ^ 1) * 16384, p[4 * s], p[4 * s + 1], p[4 * s + 2], p[4 * s + 3]);
    }
    PROFC(5);
}

#define PFW0 4
#define PACE_H 350
#define PACE_V 500
#define R8_AT 0
#define PFC0 8
__global__ void __cluster_dims__(2, 1, 1) __launch_bounds__(384, 1)
fused_kernel(const __grid_constant__ CUtensorMap mapB, const __grid_constant__ CUtensorMap mapX,
             const __grid_constant__ CUtensorMap mapXs, const __grid_constant__ CUtensorMap mapU0,
             const __grid_constant__ CUtensorMap mapU2, const __grid_constant__ CUtensorMap mapXe,
             const __grid_constant__ CUtensorMap mapCre, const __grid_constant__ CUtensorMap mapCim,
             const __grid_constant__ CUtensorMap mapV, const __grid_constant__ CUtensorMap mapO,
             const __grid_constant__ CUtensorMap mapH, const __grid_constant__ CUtensorMap mapWr,
             const __grid_constant__ CUtensorMap mapWi,
             const __grid_constant__ Params P) {
    extern __shared__ __align__(1024) uint8_t sm[];
    const uint32_t sb = smem_u32(sm);
    const uint32_t bars = sb + OFF_BAR, prog = sb + OFF_REL + 20;
    const int b = P.perm[blockIdx.x >> 1] * 2 + (blockIdx.x & 1), tid = threadIdx.x, warp = __shfl_sync(0xffffffffu, tid >> 5, 0), lane = tid & 31;
    const bool main_cta = b < 128;
    if (b == 129) return;
    const int b2 = ((b & 6) + ((b >> 4) & 1)) * 16 + (b & 8) + (b >> 5) * 2 + (b & 1);

    const int cls = b == 128 ? 128 : (b & 31) ? (b & 31) + 64 * (b >> 5) : (b == 64 ? 32 : b == 32 ? 64 : b);
    auto g1_stage = [](int it) { return it & 3; };
    auto load_w = [&]() {
        const uint32_t bw = bars + 8 * BAR_W;
        mbar_expect_tx(bw, 49152);
#pragma unroll
        for (int i = 0; i < 4; i++)
            tma_load_3d(sb + OFF_W + (i >> 1) * 9216 + (i & 1) * 18432, &mapWr + (i & 1), bw, 0, (1026 * (i < 2 ? cls : (256 - cls) & 255)) >> 7, 0);
        bulk_load(sb + OFF_F, c_tab + 2048, 12288, bw);
    };
    auto load_g1 = [&](int it, int sg) {
        const uint32_t full = bars + 8 * (BAR_FULL + sg), st = sb + sg * STAGE_BYTES;
        mbar_expect_tx(full, STAGE_BYTES);
        tma_load_4d(st, &mapB, full, it * 64, 0, 0, (b & 15) * 8);
        tma_load_4d(st + 16384, &mapX, full, it * 64, 0, 0, (b >> 4) * 128);
    };
    auto load_c = [&](int k, int s) {
        const uint32_t full = bars + 8 * (BAR_FULL2 + s);
        mbar_expect_tx(full, 32768);
        tma_load_3d(sb + OFF_B2 + s * 16384, &mapCre + (k >> 4), full, 0, k < 32 ? (b2 & 14) * 64 : (k & 15) * 64, k < 32 ? k & 15 : b2 & ~1);
    };
    auto load_h = [&](int k, int s) {
        const uint8_t* src = k < 32 ? g_hT + (k * 8 + (b2 >> 4)) * 32768 : (const uint8_t*)c_inv + (k - 32) * 32768;
        bulk_load(sb + OFF_A2 + s * 16384, src + (b & 1) * 16384, 16384, bars + 8 * (BAR_FULL2 + s));
    };
    if (elect()) {
        asm volatile("prefetch.tensormap [%0];" :: "l"(&mapB + warp) : "memory");
        if (warp == 11) PROFG(0);
        if (warp == 8) {
            PROF(0);
#pragma unroll
            for (int i = 0; i < NBAR; i++) mbar_init(bars + 8 * i, i < BAR_G1 ? 1 : i < BAR_H ? 2 : i < BAR_CD ? 4 : i < BAR_C ? 8 : 128);
            *(uint4*)(sm + OFF_REL) = make_uint4(0, 0, 0, 0);
            *(uint2*)(sm + OFF_REL + 16) = make_uint2(0, 0);
            fence_barrier_init();
            fence_proxy_async_smem();
            if (main_cta) {
#pragma unroll 1
                for (int it = 0; it < 4; it++) load_g1(it, it);
            } else load_w();
            PROF(27);
        }
    }
    __syncthreads();
    auto load_epoch = [&]() {
        unsigned e;
        asm volatile("ld.relaxed.gpu.global.u32 %0, [%1];" : "=r"(e) : "l"(&g_cnt[CNT_EPOCH * 32]));
        return e + 1;
    };
    const int g = lane >> 2, q = lane & 3;

    if (warp < 8) {
        reg_alloc<192>();
        if (tid == 0) PROF(28);
        const int wg = warp >> 2;
        unsigned epoch = 0;
        auto release = [&](int s) -> bool {
            if (warp & 3) return false;
            unsigned old = 0;
            if (elect()) asm volatile("atom.relaxed.cta.shared.inc.u32 %0, [%1], 1;" : "=r"(old) : "r"(sb + OFF_REL + 4 * s) : "memory");
            return __any_sync(0xffffffffu, old == 1);
        };
        if (main_cta) {
            float acc[128];
            const int tc = b >> 4;
            const int pp = (b & 15) * 64 + (tid >> 2);
            const bf16 lr_ = P.lam_re[pp], li_ = P.lam_im[pp], ld_ = P.log_dt[pp];
            const int gn = 16 * (b & 15) + 2 * warp + (lane >> 4);
            const uint32_t goff = 16384 + gn * 128 + ((((lane & 15) >> 1) ^ (gn & 7)) << 4) + (lane & 1) * 8;
            const uint2* gwp = (const uint2*)P.gate_w + (lane & 15);
            uint2 gw = __ldg(gwp);
            float gs = 0.f;
            float2 lam1, lam8, lam64, lam128, wq, w4, l64q;
            float m00, m01, m10, m11, sg2;
#pragma unroll 1
            for (int it = 0; it < 16; it++) {
                const int sg = g1_stage(it);
                mbar_wait(bars + 8 * (BAR_FULL + sg), (it >> 2) & 1);
                if (tid == 0) PROFK(it);
                const uint32_t st = sb + sg * STAGE_BYTES;
                const uint64_t da = make_desc(st + wg * 8192, 16, 1024), db = make_desc(st + 16384, 16, 1024);
                uint2 xv = lds64u(st + goff);
                wgmma_fence();
#pragma unroll
                for (int j = 0; j < 4; j++) wgmma_n256(acc, da + 2 * j, db + 2 * j, (it | j) != 0);
                wgmma_commit();
                xv.x = bf_mul2(xv.x, gw.x); xv.y = bf_mul2(xv.y, gw.y);
                gs += (bf_lo(xv.x) + bf_hi(xv.x)) + (bf_lo(xv.y) + bf_hi(xv.y));
                gw = __ldg(gwp + ((it + 1) & 15) * 16);
                wgmma_wait<1>();
                if (it > 0 && it < 14 && release(g1_stage(it - 1)) && elect()) {
                    if (it == 13) load_w();
                    else load_g1(it + 3, g1_stage(it - 1));
                    asm volatile("st.volatile.shared.u32 [%0], %1;" :: "r"(prog), "r"(it) : "memory");
                }
                if (warp == 1 && elect()) {
                    if ((unsigned)(it - PFW0) < 4) bulk_prefetch_l2(((it & 1) ? P.w_i : P.w_r) + (size_t)(2 * b + (((it - PFW0) >> 1) & 1)) * 4104, 8208);
                    if ((unsigned)(it - PFC0) < 8) bulk_prefetch_l2(((b & 1) ? P.c_im : P.c_re) + (size_t)(b >> 1) * 16384 + (it - PFC0) * 2048, 4096);
                }
                __syncwarp();
            }
            reg_alloc<200>();
            epoch = load_epoch();
            {
                const float lr = __bfloat162float(lr_), li = __bfloat162float(li_);
                const float dt = bf_round(expf(__bfloat162float(ld_)));
                const float mag = expf(dt * lr);
                float sn, cs; sincospif(dt * li * 0.31830988618379067f, &sn, &cs);
                lam1 = make_float2(mag * cs, mag * sn);
                const float inv = 1.f / (lr * lr + li * li);
                const float2 coef = cmul(make_float2(lam1.x - 1.f, lam1.y), make_float2(lr * inv, -li * inv));
                m00 = coef.x; m01 = -coef.y; m10 = -coef.y; m11 = -coef.x; sg2 = -1.f;
                if (P.swapB) { lam1.y = -lam1.y; m00 = -coef.y; m01 = coef.x; m10 = -coef.x; m11 = -coef.y; sg2 = 1.f; }
                float2 z = cmul(lam1, lam1);
                z = cmul(z, z); lam8 = cmul(z, z);
                z = cmul(lam8, lam8); z = cmul(z, z);
                lam64 = cmul(z, z); lam128 = cmul(lam64, lam64);
                const float2 l256 = cmul(lam128, lam128), l512 = cmul(l256, l256);
                w4 = cmul(l512, l512);
                const float2 one = make_float2(1.f, 0.f);
                wq = cmul((q & 1) ? l256 : one, (q & 2) ? l512 : one);
                l64q = cmul((q & 1) ? lam64 : one, (q & 2) ? lam128 : one);
            }
#pragma unroll
            for (int o = 1; o < 16; o <<= 1) gs += __shfl_xor_sync(0xffffffffu, gs, o);
            {
                const float gg = bf_round(__fdividef(1.f, 1.f + __expf(-bf_round(gs))));
                if ((lane & 15) == 0) *(uint2*)(sm + OFF_GS + (2 * warp + (lane >> 4)) * 8) = make_uint2(__float_as_uint(gg), __float_as_uint(2.f * bf_round(1.f - gg)));
            }
            const uint4 *ap = &g_agg[(tc - 1 - q) * 1024 + pp], *ap1 = q + 5 <= tc ? ap - 4096 : ap;
            if (q + 5 > tc) w4 = make_float2(0.f, 0.f);
            asm volatile("st.volatile.shared.v4.f32 [%0], {%1, %2, %3, %4};" :: "r"(sb + OFF_DUMMY), "f"(lam64.x + lam128.x + w4.x), "f"(wq.x + l64q.x + m00),
                         "f"(lam64.y + lam128.y + w4.y), "f"(wq.y + l64q.y + m01 + __uint_as_float((uint32_t)(size_t)ap1)) : "memory");
            wgmma_wait_all(acc);
            if ((tid & 127) == 0) mbar_arrive(bars + 8 * BAR_G1);
            if (tid == 0) PROF(3);
            if (tid == 128) PROF(25);
            PROFS(0);
            float2 ag[8];
#pragma unroll
            for (int c = 0; c < 8; c++) ag[c] = make_float2(acc[16 * c], acc[16 * c + 2]);
#pragma unroll
            for (int r = 1; r < 8; r++)
#pragma unroll
                for (int c = 0; c < 8; c++) {
                    const int i = 16 * c + 4 * (r >> 1) + (r & 1);
                    ag[c] = cfma(lam1, ag[c], make_float2(acc[i], acc[i + 2]));
                }
            float2 v = ag[0];
#pragma unroll
            for (int c = 1; c < 8; c++) v = cfma(lam8, v, ag[c]);
            {
                float2 n = make_float2(__shfl_up_sync(0xffffffffu, v.x, 1, 4), __shfl_up_sync(0xffffffffu, v.y, 1, 4));
                if (q >= 1) v = cfma(lam64, n, v);
                n = make_float2(__shfl_up_sync(0xffffffffu, v.x, 2, 4), __shfl_up_sync(0xffffffffu, v.y, 2, 4));
                if (q >= 2) v = cfma(lam128, n, v);
            }
            if (q == 3 && tc < 7) {
                asm volatile("st.relaxed.gpu.global.v4.u32 [%0], {%1, %2, %3, %4};"
                    :: "l"(ap + 4096), "r"(__float_as_uint(v.x)), "r"(epoch), "r"(__float_as_uint(v.y)), "r"(epoch) : "memory");
            }
            uint4 r0, r1;
            auto poll = [&]() {
                asm volatile("ld.relaxed.gpu.global.v4.u32 {%0, %1, %2, %3}, [%8];\n"
                             "ld.relaxed.gpu.global.v4.u32 {%4, %5, %6, %7}, [%9];"
                    : "=r"(r0.x), "=r"(r0.y), "=r"(r0.z), "=r"(r0.w), "=r"(r1.x), "=r"(r1.y), "=r"(r1.z), "=r"(r1.w) : "l"(ap), "l"(ap1) : "memory");
            };
            if (q < tc) poll();
            PROFS(1);
            float2 ex = make_float2(__shfl_up_sync(0xffffffffu, v.x, 1, 4), __shfl_up_sync(0xffffffffu, v.y, 1, 4));
            if (q == 0) ex = make_float2(0.f, 0.f);
            {
                uint32_t z;
                asm volatile("ld.volatile.shared.u32 %0, [%1];" : "=r"(z) : "r"(prog) : "memory");
                z >>= 16;
                m00 = __uint_as_float(__float_as_uint(m00) | z); m01 = __uint_as_float(__float_as_uint(m01) | z);
                m10 = __uint_as_float(__float_as_uint(m10) | z); m11 = __uint_as_float(__float_as_uint(m11) | z);
            }
            auto scale = [&](float& x, float& y) { const float u = fmaf(m00, x, m01 * y); y = fmaf(m10, x, m11 * y); x = u; };
#pragma unroll
            for (int i = 0; i < 128; i += 4) { scale(acc[i], acc[i + 2]); scale(acc[i + 1], acc[i + 3]); }
#pragma unroll
            for (int c = 0; c < 7; c++) { scale(ag[c].x, ag[c].y); asm volatile("" : "+f"(ag[c].x), "+f"(ag[c].y)); }
#pragma unroll
            for (int i = 0; i < 128; i++) asm volatile("" : "+f"(acc[i]));
            {
                float2 part = make_float2(0.f, 0.f);
                PROFS(2);
                if (q < tc) {
                    for (unsigned n = 0; (r0.y != epoch || r0.w != epoch || r1.y != epoch || r1.w != epoch) && n < SPIN_LIMIT; n++) poll();
                    part = cfma(w4, make_float2(__uint_as_float(r1.x), __uint_as_float(r1.z)), make_float2(__uint_as_float(r0.x), __uint_as_float(r0.z)));
                    part = cmul(wq, part);
                }
                __syncwarp();
                part.x += __shfl_xor_sync(0xffffffffu, part.x, 1); part.y += __shfl_xor_sync(0xffffffffu, part.y, 1);
                part.x += __shfl_xor_sync(0xffffffffu, part.x, 2); part.y += __shfl_xor_sync(0xffffffffu, part.y, 2);
                ex = cfma(l64q, part, ex);
            }
            if (tid == 0) PROF(4);
            PROFS(3);
            scale(ex.x, ex.y);
            lam1.y *= sg2; lam8.y *= sg2;
#pragma unroll
            for (int c = 0; c < 8; c++) { const float2 n = cfma(lam8, ex, ag[c]); ag[c] = ex; ex = n; }
            mbar_wait(bars + 8 * BAR_G1, 0);
#pragma unroll
            for (int r = 0; r < 8; r++) {
#pragma unroll
                for (int c = 0; c < 8; c++) {
                    const int i = 16 * c + 4 * (r >> 1) + (r & 1);
                    ag[c] = cfma(lam1, ag[c], make_float2(acc[i], acc[i + 2]));
                }
                const uint32_t hs = sb + OFF_HS + wg * 14336 + ((tid * 16) ^ ((tid << 1) & 48)) + r * 2048;
                sts128u(hs + 32768, pack2(ag[0].x, ag[4].x), pack2(ag[1].x, ag[5].x), pack2(ag[2].x, ag[6].x), pack2(ag[3].x, ag[7].x));
                sts128u(hs, pack2(ag[0].y, ag[4].y), pack2(ag[1].y, ag[5].y), pack2(ag[2].y, ag[6].y), pack2(ag[3].y, ag[7].y));
                if (r & 1) {
                    fence_proxy_async_smem();
                    __syncwarp();
                    if (lane == 0) mbar_arrive(bars + 8 * (BAR_H + 5 * wg + (r >> 1)));
                }
            }
            if (tid == 0) PROF(5);
            PROFS(4);
        }
        mbar_wait(bars + 8 * BAR_C, 0);
        if (tid == 0) PROF(6);
        PROFS(5);
        phase_c(sb, b == 0 ? (8 - warp) & 7 : 7 - warp, warp, lane);
        fence_proxy_async_smem();
        __syncwarp();
        if (lane == 0) mbar_arrive(bars + 8 * BAR_CD);
        if (tid == 0) PROF(7);
        PROFS(6);
        PROFC(6);
        {
            float acc[64], acc2[64];
            uint32_t dk[16];
#pragma unroll
            for (int j = 0; j < 16; j++) dk[j] = ldg32u(P.dskip + (b2 & 14) * 64 + 2 * q + 8 * j);
            const int trow = 64 * (16 * (b & 1) + 2 * warp) + 32 * (g & 1) + 8 * (g >> 1) + (b2 >> 4);
            int s = 3, sp = 0, k = 0; uint32_t ph = 0;
            auto steps = [&](int lim) {
#pragma unroll 1
                for (; k < lim; k++) {
                    mbar_wait(bars + 8 * (BAR_FULL2 + s), ph);
                    if (tid == 0 && k == 0) PROF(16);
                    if (tid == 0 && (k & 1) == 0) PROFK(16 + (k >> 1));
                    const uint64_t da = make_desc(sb + OFF_A2 + s * 16384 + wg * 8192, 4096, 512, 2), db = make_desc(sb + OFF_B2 + s * 16384, 16, 1024);
                    wgmma_fence();
#pragma unroll
                    for (int j = 0; j < 4; j++) wgmma_n128<0>(acc, da + 64 * j, db + 2 * j, (k | j) != 0);
                    wgmma_commit();
                    wgmma_wait<1>();
                    if (k > 0 && lane == 0) mbar_arrive(bars + 8 * (BAR_EMPTY2 + sp));
                    __syncwarp();
                    sp = s;
                    if (s == 2) ph ^= 1;
                    if (++s == 5) s = 0;
                }
            };
            steps(main_cta ? R8_AT + 2 * wg : 0);
            mbar_wait(bars + 8 * BAR_CD, 0);
            radix8(sb, sb + OFF_G + 512, wg, warp & 3, lane, 5 + wg);
            fence_proxy_async_smem();
            __syncwarp();
            if (lane == 0) mbar_arrive(bars + 8 * (BAR_H + 5 * wg + 4));
            if (tid == 0) PROF(24);
            if (main_cta) {
            steps(32);
            const float2* gp = (const float2*)&g_gate[(trow & ~255) + ((trow & 62) << 2) + ((trow >> 5) & 6) + (trow & 1)];
            const float2 g0 = __ldcg(gp), g1 = __ldcg(gp + 2);
            if (wg) asm volatile("bar.sync 3, 256;" ::: "memory");
#pragma unroll
            for (int k = 0; k < 4; k++) {
                const int s = k;
                mbar_wait(bars + 8 * (BAR_FULL2 + s), k == 3);
                const uint64_t da = make_desc(sb + OFF_A2 + s * 16384 + wg * 8192, 4096, 512, 2), db = make_desc(sb + OFF_B2 + s * 16384, 8192, 1024);
                wgmma_fence();
#pragma unroll
                for (int j = 0; j < 4; j++) wgmma_n128<1>(acc2, da + 64 * j, db + 128 * j, (k | j) != 0);
                wgmma_commit();
            }
            if (!wg) asm volatile("bar.arrive 3, 256;" ::: "memory");
            const uint32_t ob = sb + (wg ? 0 : OFF_U) + (warp & 3) * 8192, rr = 2 * (g & 3) + (g >> 2);
            const uint32_t xrow = 4 * (lane & 1) + ((lane >> 1) & 3);
            const uint32_t xb = sb + wg * 16384 + ((warp & 3) * 16 + (lane & 8) + xrow) * 128 + (((lane >> 4) ^ xrow) << 4);
            wgmma_wait<4>();
#pragma unroll
            for (int i = 0; i < 64; i++) asm volatile("" : "+f"(acc[i]) :: "memory");
            mbar_wait(bars + 8 * BAR_X, 1);
#pragma unroll
            for (int j = 0; j < 16; j += 2) {
                uint32_t xv[4];
                ldsm_x4(xv, (xb ^ ((j & 7) << 4)) + (j >> 3) * 8192);
#pragma unroll
                for (int i = 0; i < 4; i++) {
                    const uint32_t p = bf_mul2(xv[i], dk[j + (i >> 1)]);
                    const float sc = (i & 1) ? g1.y : g0.y;
                    acc[4 * j + 2 * i] = sc * fmaf(bf_lo(p), 0.5f, acc[4 * j + 2 * i]);
                    acc[4 * j + 2 * i + 1] = sc * fmaf(bf_hi(p), 0.5f, acc[4 * j + 2 * i + 1]);
                }
            }
            if (wg) asm volatile("bar.sync 4, 256;" ::: "memory");
            else asm volatile("bar.arrive 4, 256;" ::: "memory");
            wgmma_wait_all(acc2);
            if (tid == 0) PROF(17);
            if (tid == 128) PROF(18);
            const uint32_t oa = ob + rr * 128 + (((q >> 1) ^ rr) << 4) + (q & 1) * 8;
#pragma unroll
            for (int c = 0; c < 4; c++) {
#pragma unroll
                for (int j = 0; j < 4; j++) {
                    const int i = 16 * c + 4 * j;
                    sts64((oa ^ (j << 5)) + c * 2048, fmaf(g0.x, acc2[i], acc[i]), fmaf(g0.x, acc2[i + 1], acc[i + 1]));
                    sts64((oa ^ (j << 5)) + c * 2048 + 1024, fmaf(g1.x, acc2[i + 2], acc[i + 2]), fmaf(g1.x, acc2[i + 3], acc[i + 3]));
                }
                fence_proxy_async_smem();
                __syncwarp();
                if (elect()) tma_store_5d(&mapO, ob + c * 2048, (b2 >> 4) * 1024 + (b2 & 14) * 64 + 32 * c, 16 * (b & 1) + 2 * warp);
            }
            if (elect()) {
                bulk_commit();
                asm volatile("cp.async.bulk.wait_group.read 0;" ::: "memory");
            }
            if (tid == 0) PROF(19);
            if (tid == 224) { PROF(20); PROFG(4); }
            }
        }
        if (tid == 0) {
            const unsigned old = atomicAdd(&g_cnt[CNT_DONE * 32], 1u);
            if (old == 128) { g_cnt[CNT_DONE * 32] = 0; g_cnt[CNT_EPOCH * 32] = load_epoch(); }
        }
    } else {
        reg_dealloc<120>();
        const int t = tid - 256, w = warp - 8;
        if (w == 0 && main_cta && elect()) {
            mbar_expect_tx(bars + 8 * BAR_X, 32768);
            tma_load_4d(sb + OFF_U, &mapXs, bars + 8 * BAR_X, (b & 15) * 64, 0, 0, b >> 4);
            tma_load_4d(sb + OFF_U + 16384, &mapXs, bars + 8 * BAR_X, (b & 15) * 64 + 32, 0, 0, b >> 4);
            asm volatile("prefetch.tensormap [%0];" :: "l"(&mapWi) : "memory");
        }
        const unsigned epoch = load_epoch();
        const bool real_cls = (cls & 127) == 0;
        const bool special = t < 4;
        const float R = 0.70710678118654752f;
        uint4 fa[4];
#pragma unroll
        for (int i = 0; i < 4; i++) fa[i] = __ldg((const uint4*)c_tab + i * 128 + t);
        float2 w1, w2, w3;
        {
            const int kk = (t >> 3) & 7, r = t & 7;
            float sn, cs;
            sincospif((float)(((cls + 256 * kk) * r) & 2047) * (1.f / 1024.f), &sn, &cs);
            sn *= 1.f / 1024.f; cs *= 1.f / 1024.f;
            const uint32_t gf = sb + OFF_G + kk * 16 + r * 2, gi = sb + OFF_G + 512 + r * 16 + kk * 2;
            if (t < 64) {
                sts16(gf, cs); sts16(gf + 128, real_cls ? 0.f : sn); sts16(gf + 256, -sn); sts16(gf + 384, real_cls ? 0.f : cs);
                sts16(gi, cs); sts16(gi + 128, -sn); sts16(gi + 256, sn); sts16(gi + 384, cs);
            }
            sincospif((float)(8 * w + g) * (1.f / 128.f), &sn, &cs);
            w1 = make_float2(cs, -sn); w2 = cmul(w1, w1); w3 = cmul(w1, w2);
        }
        if (main_cta) {
            const uint32_t ua = sb + OFF_U + (lane >> 4) * 8192 + (8 * w + (lane & 7)) * 64 + ((((lane >> 3) & 1) ^ ((lane >> 1) & 3)) << 4);
            mbar_wait(bars + 8 * BAR_X, 0);
            if (t == 0) PROF(8);
#pragma unroll 1
            for (int hf = 0; hf < 2; hf++) {
                float acc[64];
                const uint64_t db = make_desc(sb + OFF_U + hf * 16384, 4096, 512, 2);
                wgmma_fence();
                wgmma_rs_n128<0>(acc, fa[0], db); wgmma_rs_n128<1>(acc, fa[1], db + 64); wgmma_rs_n128<1>(acc, fa[2], db + 128); wgmma_rs_n128<1>(acc, fa[3], db + 192);
                wgmma_commit();
                wgmma_wait_all(acc);
                helper_sync();
#pragma unroll
                for (int jp = 0; jp < 2; jp++) {
                    float2 y[4][4];
#pragma unroll
                    for (int i = 0; i < 4; i++) {
                        const int o = 8 * jp + 4 * (i >> 1) + (i & 1);
#pragma unroll
                        for (int m = 0; m < 4; m++) y[i][m] = make_float2(acc[16 * m + o], acc[16 * m + o + 2]);
                    }
                    if (special) {
#pragma unroll
                        for (int i = 0; i < 4; i++) {
                            const float2 s0 = cadd(y[i][0], y[i][2]), s1 = csub(y[i][0], y[i][2]), s2 = cadd(y[i][1], y[i][3]), s3 = csub(y[i][1], y[i][3]);
                            const float b0 = y[i][0].y, b2 = y[i][2].y;
                            y[i][0] = make_float2(s0.x + s2.x, s0.x - s2.x);
                            y[i][1] = make_float2(s1.x, -s3.x);
                            y[i][2] = make_float2(fmaf(R, s3.y, b0), fmaf(-R, s2.y, -b2));
                            y[i][3] = make_float2(fmaf(-R, s3.y, b0), fmaf(-R, s2.y, b2));
                        }
                    } else {
#pragma unroll
                        for (int i = 0; i < 4; i++) {
                            y[i][1] = cmul(y[i][1], w1); y[i][2] = cmul(y[i][2], w2); y[i][3] = cmul(y[i][3], w3);
                            fft4(y[i][0], y[i][1], y[i][2], y[i][3]);
                        }
                    }
                    __syncwarp();
#pragma unroll
                    for (int c = 0; c < 4; c++)
                        stsm_x4((ua ^ (jp * 32)) + hf * 16384 + c * 2048, pack2(y[0][c].x, y[1][c].x), pack2(y[2][c].x, y[3][c].x),
                                pack2(y[0][c].y, y[1][c].y), pack2(y[2][c].y, y[3][c].y));
                }
                fence_proxy_async_smem();
                helper_sync();
                if (w == 0 && elect()) {
                    tma_store_4d(&mapU0, sb + OFF_U + hf * 16384, (b & 15) * 64 + hf * 32, 0, 0, b >> 4);
                    bulk_commit();
                }
            }
        }
        reg_dealloc<104>();
        if (w == 0 && elect()) {
            PROF(21);
            if (main_cta) {
                bulk_wait0();
                signal_counter(&g_cnt[CNT_U * 32]);
            }
            PROF(9);
            mbar_expect_tx(bars + 8 * BAR_U, 32768);
            wait_counter(&g_cnt[CNT_U * 32], epoch * 128);
            PROF(11);
#pragma unroll 1
            for (int i = 0; i < 2; i++) {
#pragma unroll
                for (int j = 0; j < 4; j++)
                    tma_load_4d(sb + OFF_U + i * 16384 + j * 4096, &mapU2, bars + 8 * BAR_U, 0, 0, j * 4, b == 128 ? 1 : b == 0 ? 0 : 2 * b + i);
            }
        }
        fence_proxy_async_smem();
        helper_sync();
        mbar_wait(bars + 8 * BAR_U, 0);
        if (t == 0) PROF(23);
#pragma unroll 1
        for (int hf = 0; hf < 2; hf++) radix8(sb, sb + OFF_G, hf, w, lane, 1);
        if (t == 0) PROF(22);
        mbar_wait(bars + 8 * BAR_W, 0);
        if (t == 0) PROF(10);
#pragma unroll 1
        for (int rr = 0; rr < 2; rr++) {
            const int row = 2 * w + rr;
            const uint32_t dp = sb + OFF_W + row * 1152, mp = sb + OFF_W + 9216 + (b == 0 ? (8 - row) & 7 : 7 - row) * 1152;
            const uint32_t od = dp + ((1026 * cls) & 127), om = mp + ((1026 * (256 - cls)) & 127);
            uint32_t v[2][16][2], e[2][2];
#pragma unroll
            for (int pl = 0; pl < 2; pl++) {
#pragma unroll
                for (int i = 0; i < 8; i++) {
                    const uint32_t a = od + 4 * lane + pl * 18432 + 128 * i, c = om - 4 * lane + pl * 18432 + 1024 - 128 * i;
                    v[pl][i][0] = lds16(a); v[pl][i][1] = lds16(a + 2);
                    v[pl][8 + i][0] = lds16(c); v[pl][8 + i][1] = lds16(c - 2);
                }
                e[pl][0] = lds16(om + pl * 18432); e[pl][1] = lds16(od + pl * 18432 + 1024);
            }
            __syncwarp();
#pragma unroll
            for (int pl = 0; pl < 2; pl++) {
                if (lane == 0) {
                    v[pl][0][0] = pack2(fmaf(pl ? -0.5f : 0.5f, bf_lo(e[pl][0]), 0.5f * bf_lo(v[pl][0][0])), 0.f);
                    v[pl][8][0] = pack2(fmaf(pl ? -0.5f : 0.5f, bf_lo(e[pl][1]), 0.5f * bf_lo(v[pl][8][0])), 0.f);
                }
#pragma unroll
                for (int i = 0; i < 16; i++)
                    sts32((i < 8 ? dp : mp) + pl * 18432 + (i & 7) * 128 + ((lane * 4) ^ ((i & 3) << 4)),
                          __byte_perm(v[pl][i][0], v[pl][i][1], 0x5410) ^ (pl && i >= 8 ? 0x80008000u : 0u));
            }
        }
        mbar_arrive(bars + 8 * BAR_C);
        if (t == 0) PROF(12);
        if (elect()) {
            if ((w & 1) == 0) {
                const int hf = w >> 1;
                const uint32_t bh = bars + 8 * (BAR_H + 5 * hf);
                if (main_cta) {
#pragma unroll
                    for (int i = 0; i < 8; i++) {
                        if (i < 4) mbar_wait(bh + 8 * i, 0);
                        if (i > 4) pause(PACE_H);
                        if (i == 0 && hf) PROF(29);
                        if (i == 3 && hf) PROF(30);
                        tma_store_3d(&mapH, sb + OFF_HS + (i < 4 ? 32768 : 0) + hf * 16384 + (i & 3) * 4096, 0, (b >> 4) * 2 + hf, (i >> 2) * 128 + (b & 15) * 8 + (i & 3) * 2);
                        if (i == 0) bulk_store(g_gate + 16 * b + 8 * hf, sb + OFF_GS + 64 * hf, 64);
                        if ((i & 3) == 3) {
                            bulk_commit();
                            bulk_wait0();
                            signal_counter(&g_cnt[(CNT_H + (i >> 2)) * 32]);
                            if (hf) PROF(i < 4 ? 26 : 2);
                        }
                    }
                    mbar_arrive(bars + 8 * BAR_HF);
                }
                mbar_wait(bh + 32, 0);
#pragma unroll
                for (int i = 0; i < 4; i++) {
                    if (i == 2 && real_cls) break;
                    if (i) pause(PACE_V);
                    tma_store_4d(&mapU2, sb + OFF_U + (i >> 1) * 16384 + hf * 8192 + (i & 1) * 4096, 0, 0, hf * 8 + (i & 1) * 4, b == 128 ? 1 : 2 * b + (i >> 1));
                }
                bulk_commit();
                bulk_wait0();
                signal_counter(&g_cnt[CNT_V * 32]);
                if (hf) PROF(13);
            } else if (main_cta && w == 1) {
                mbar_wait(bars + 8 * BAR_G1, 0);
#pragma unroll 1
                for (int k = 0; k < 5; k++) load_c(k, k < 2 ? k + 3 : k - 2);
                wait_counter(&g_cnt[CNT_H * 32], epoch * 256);
                PROF(1);
#pragma unroll
                for (int k = 0; k < 5; k++) {
                    if (k == 2) mbar_wait(bars + 8 * BAR_CD, 0);
                    if (k == 3) mbar_wait(bars + 8 * BAR_HF, 0);
                    load_h(k, k < 2 ? k + 3 : k - 2);
                }
                int s = 3; uint32_t ph = 0;
#pragma unroll 1
                for (int k = 5; k < 36; k++) {
                    if ((k & 15) == 0) mbar_wait(bars + 8 * (BAR_H1 - 1 + (k >> 4)), 0);
                    mbar_wait(bars + 8 * (BAR_EMPTY2 + s), ph);
                    load_c(k, s);
                    load_h(k, s);
                    if (s == 2) ph ^= 1;
                    if (++s == 5) s = 0;
                }
            } else if (main_cta) {
                bulk_prefetch_l2(c_inv + b * 128, 1024);
                mbar_wait(bars + 8 * BAR_CD, 0);
                mbar_expect_tx(bars + 8 * BAR_X, 32768);
                tma_load_3d(sb, &mapXe, bars + 8 * BAR_X, 0, 128 * (b & 1), b2 & ~1);
                tma_load_3d(sb + 16384, &mapXe, bars + 8 * BAR_X, 0, 128 * (b & 1) + 64, b2 & ~1);
                wait_counter(&g_cnt[(CNT_H + 1) * 32], epoch * 256);
                mbar_arrive(bars + 8 * BAR_H1);
                wait_counter(&g_cnt[CNT_V * 32], epoch * 258);
                mbar_arrive(bars + 8 * BAR_V);
                PROF(14);
            }
        }
    }
}

typedef CUresult (*PFN_encodeTiled)(CUtensorMap*, CUtensorMapDataType, cuuint32_t, void*, const cuuint64_t*, const cuuint64_t*,
                                    const cuuint32_t*, const cuuint32_t*, CUtensorMapInterleave, CUtensorMapSwizzle,
                                    CUtensorMapL2promotion, CUtensorMapFloatOOBfill);

static CUtensorMap make_map(PFN_encodeTiled enc, const void* ptr, int rank, const cuuint64_t* dims, const cuuint64_t* strides, const cuuint32_t* box,
                            CUtensorMapSwizzle sw = CU_TENSOR_MAP_SWIZZLE_128B, CUtensorMapDataType dt = CU_TENSOR_MAP_DATA_TYPE_BFLOAT16) {
    CUtensorMap m;
    cuuint32_t es[5] = {1, 1, 1, 1, 1};
    enc(&m, dt, rank, (void*)ptr, dims, strides, box, es, CU_TENSOR_MAP_INTERLEAVE_NONE,
        sw, CU_TENSOR_MAP_L2_PROMOTION_L2_128B, CU_TENSOR_MAP_FLOAT_OOB_FILL_NONE);
    return m;
}

extern "C" void kernel_launch(void* const* d_in, const int* in_sizes, int n_in, void* d_out, int out_size) {
    const bf16* x = (const bf16*)d_in[0];
    const bf16* wr = (const bf16*)d_in[1];
    const bf16* wi = (const bf16*)d_in[2];
    const bf16* Bre = (const bf16*)d_in[6];
    const bf16* Bim = (const bf16*)d_in[7];
    const bf16* Cre = (const bf16*)d_in[8];
    const bf16* Cim = (const bf16*)d_in[9];

    void* fn = nullptr;
    cudaDriverEntryPointQueryResult st;
    cudaGetDriverEntryPoint("cuTensorMapEncodeTiled", &fn, cudaEnableDefault, &st);
    PFN_encodeTiled enc = (PFN_encodeTiled)fn;
    void *p_hT, *p_U;
    cudaGetSymbolAddress(&p_hT, g_hT);
    cudaGetSymbolAddress(&p_U, g_U);

    Params P;
    P.lam_re = (const bf16*)d_in[4]; P.lam_im = (const bf16*)d_in[5]; P.log_dt = (const bf16*)d_in[10];
    P.dskip = (const bf16*)d_in[11]; P.gate_w = (const bf16*)d_in[12]; P.c_re = Cre; P.c_im = Cim; P.w_r = wr; P.w_i = wi;
    P.swapB = Bim < Bre;

    for (int c = 0; c < 68; c++) P.perm[c] = c < 4 ? 32 + 8 * c : c < 36 ? ((c - 4) & 24) + ((c - 5) & 7) : c < 64 ? 32 + (c - 36) / 7 * 8 + ((c - 37 + 7) % 7 + 1) : c;

    CUtensorMap mB, mX, mCre, mCim, mXs, mU0, mV, mU2, mXe, mO, mH, mWr, mWi;
    {
        cuuint64_t d[3] = {64, 2052, 8}, s[2] = {128, 262656};
        cuuint32_t bx[3] = {64, 9, 8};
        mWr = make_map(enc, wr, 3, d, s, bx, CU_TENSOR_MAP_SWIZZLE_NONE);
        mWi = make_map(enc, wi, 3, d, s, bx, CU_TENSOR_MAP_SWIZZLE_NONE);
    }
    {
        cuuint64_t d[3] = {256, 16, 256}, s[2] = {2048, 32768};
        cuuint32_t bx[3] = {256, 1, 2};
        mH = make_map(enc, p_hT, 3, d, s, bx, CU_TENSOR_MAP_SWIZZLE_NONE, CU_TENSOR_MAP_DATA_TYPE_UINT64);
    }
    {
        const bf16* lo = P.swapB ? Bim : Bre; const bf16* hi = P.swapB ? Bre : Bim;
        cuuint64_t d[4] = {1024, 8, 2, 128}, s[3] = {2048, (cuuint64_t)((const char*)hi - (const char*)lo), 16384};
        cuuint32_t bx[4] = {64, 8, 2, 8};
        mB = make_map(enc, lo, 4, d, s, bx);
    }
    {
        cuuint64_t d[4] = {1024, 2, 4, 928}, s[3] = {2048, 64 * 2048, 2 * 2048};
        cuuint32_t bx[4] = {64, 2, 4, 32};
        mX = make_map(enc, x, 4, d, s, bx);
    }
    {
        cuuint64_t d[3] = {64, 1024, 16}, s[2] = {2048, 128};
        cuuint32_t bx[3] = {64, 128, 1};
        mCre = make_map(enc, Cre, 3, d, s, bx);
        mCim = make_map(enc, Cim, 3, d, s, bx);
    }
    {
        cuuint64_t d[3] = {64, 256, 128}, s[2] = {16384, 128};
        cuuint32_t bx[3] = {64, 64, 2};
        mV = make_map(enc, p_U, 3, d, s, bx);
        mXe = make_map(enc, x, 3, d, s, bx);
    }
    {
        cuuint64_t d[5] = {8192, 2, 2, 2, 32}, s[4] = {16 * 4096, 32 * 4096, 8 * 4096, 64 * 4096};
        cuuint32_t bx[5] = {32, 2, 2, 2, 2};
        mO = make_map(enc, d_out, 5, d, s, bx, CU_TENSOR_MAP_SWIZZLE_128B, CU_TENSOR_MAP_DATA_TYPE_FLOAT32);
    }
    {
        cuuint64_t d[4] = {1024, 64, 4, 8}, s[3] = {32 * 2048, 8 * 2048, 2048};
        cuuint32_t bx[4] = {32, 64, 4, 1};
        mXs = make_map(enc, x, 4, d, s, bx, CU_TENSOR_MAP_SWIZZLE_64B);
    }
    {
        cuuint64_t d[4] = {1024, 128, 2, 8}, s[3] = {32768, 16384, 2048};
        cuuint32_t bx[4] = {32, 128, 2, 1};
        mU0 = make_map(enc, p_U, 4, d, s, bx, CU_TENSOR_MAP_SWIZZLE_64B);
    }
    {
        cuuint64_t d[4] = {64, 8, 16, 256}, s[3] = {2048, 128, 16384};
        cuuint32_t bx[4] = {64, 8, 4, 1};
        mU2 = make_map(enc, p_U, 4, d, s, bx);
    }
    cudaFuncSetAttribute(fused_kernel, cudaFuncAttributeMaxDynamicSharedMemorySize, SMEM_BYTES);
    fused_kernel<<<130, 384, SMEM_BYTES, cudaStreamPerThread>>>(mB, mX, mXs, mU0, mU2, mXe, mCre, mCim, mV, mO, mH, mWr, mWi, P);
}
```

```cpp
#include <cuda_runtime.h>
#include <cuda_bf16.h>
#include <cuda.h>
#include <stdint.h>

typedef __nv_bfloat16 bf16;

__device__ const __align__(128) uint32_t c_tab[5120] = {
0x3f803f80,0xbf803f80,0x3f803f80,0xbf803f80,0x3f803f80,0xbf803f80,0x3f803f80,0xbf803f80,0x3f803f80,0xbf803f80,0x3f803f80,0xbf803f80,
0x3f803f80,0xbf803f80,0x3f803f80,0xbf803f80,0x3f7f3f80,0xbdc98000,0x3f223f35,0xbf46bf35,0x3f753f7b,0xbe95be48,0x3ef13f0e,0xbf62bf55,
0x3f623f6d,0xbef1bec4,0x3e953ec4,0xbf75bf6d,0x3f463f55,0xbf22bf0e,0x3dc93e48,0xbf7fbf7b,0x3f7b3f80,0xbe488000,0xbe480000,0xbf7bbf80,
0x3f553f6d,0xbf0ebec4,0xbf0ebec4,0xbf55bf6d,0x3f0e3f35,0xbf55bf35,0xbf55bf35,0xbf0ebf35,0x3e483ec4,0xbf7bbf6d,0xbf7bbf6d,0xbe48bec4,
0x3f753f80,0xbe958000,0xbf62bf35,0xbef1bf35,0x3f223f55,0xbf46bf0e,0xbf7fbf7b,0x3dc9be48,0x3dc93ec4,0xbf7fbf6d,0xbf46bf6d,0x3f223ec4,
0xbef1be48,0xbf62bf7b,0xbe95bf0e,0x3f753f55,0x3f6d3f80,0xbec48000,0xbf6dbf80,0x3ec48000,0x3ec43f35,0xbf6dbf35,0xbec4bf35,0x3f6d3f35,
0xbec40000,0xbf6dbf80,0x3ec40000,0x3f6d3f80,0xbf6dbf35,0xbec4bf35,0x3f6d3f35,0x3ec43f35,0x3f623f80,0xbef18000,0xbe95bf35,0x3f753f35,
0x3dc93f0e,0xbf7fbf55,0x3f223e48,0x3f463f7b,0xbf46bec4,0xbf22bf6d,0x3f7f3f6d,0xbdc93ec4,0xbf75bf7b,0x3e95be48,0x3ef13f55,0xbf62bf0e,
0x3f553f80,0xbf0e8000,0x3f0e0000,0x3f553f80,0xbe483ec4,0xbf7bbf6d,0x3f7b3f6d,0xbe483ec4,0xbf7bbf35,0xbe48bf35,0x3e483f35,0xbf7bbf35,
0xbf0ebf6d,0x3f553ec4,0xbf55bec4,0xbf0ebf6d,0x3f463f80,0xbf228000,0x3f7f3f35,0x3dc93f35,0xbef13e48,0xbf62bf7b,0x3e953f55,0xbf75bf0e,
0xbf75bf6d,0x3e95bec4,0xbf62bec4,0xbef1bf6d,0x3dc9bf0e,0x3f7f3f55,0xbf22bf7b,0x3f463e48,0x3f353f80,0xbf358000,0x3f353f80,0xbf358000,
0xbf350000,0xbf35bf80,0xbf350000,0xbf35bf80,0xbf35bf80,0x3f358000,0xbf35bf80,0x3f358000,0x3f350000,0x3f353f80,0x3f350000,0x3f353f80,
0x3f223f80,0xbf468000,0xbdc93f35,0xbf7fbf35,0xbf62be48,0xbef1bf7b,0xbf75bf55,0x3e95bf0e,0xbe95bf6d,0x3f753ec4,0x3ef1bec4,0x3f623f6d,
0x3f7f3f0e,0x3dc93f55,0x3f463f7b,0xbf223e48,0x3f0e3f80,0xbf558000,0xbf550000,0xbf0ebf80,0xbf7bbec4,0xbe48bf6d,0xbe48bf6d,0x3f7b3ec4,
0x3e48bf35,0x3f7b3f35,0x3f7b3f35,0xbe483f35,0x3f553f6d,0xbf0e3ec4,0xbf0e3ec4,0xbf55bf6d,0x3ef13f80,0xbf628000,0xbf75bf35,0x3e95bf35,
0xbf7fbf0e,0x3dc9bf55,0x3f46be48,0x3f223f7b,0x3f22bec4,0x3f463f6d,0x3dc93f6d,0xbf7fbec4,0x3e953f7b,0xbf75be48,0xbf62bf55,0x3ef1bf0e,
0x3ec43f80,0xbf6d8000,0xbec4bf80,0x3f6d8000,0xbf6dbf35,0x3ec4bf35,0x3f6d3f35,0xbec43f35,0x3f6d0000,0x3ec43f80,0xbf6d0000,0xbec4bf80,
0xbec43f35,0xbf6dbf35,0x3ec4bf35,0x3f6d3f35,0x3e953f80,0xbf758000,0x3ef1bf35,0x3f623f35,0xbf46bf55,0x3f22bf0e,0x3dc93f7b,0xbf7fbe48,
0x3f7f3ec4,0xbdc93f6d,0xbf22bf6d,0x3f46bec4,0xbf623e48,0xbef1bf7b,0x3f753f0e,0xbe953f55,0x3e483f80,0xbf7b8000,0x3f7b0000,0x3e483f80,
0xbf0ebf6d,0x3f55bec4,0xbf553ec4,0xbf0ebf6d,0x3f553f35,0xbf0e3f35,0x3f0ebf35,0x3f553f35,0xbf7bbec4,0x3e48bf6d,0xbe483f6d,0xbf7bbec4,
0x3dc93f80,0xbf7f8000,0x3f463f35,0xbf223f35,0xbe95bf7b,0x3f75be48,0xbf62bf0e,0x3ef1bf55,0x3ef13f6d,0xbf623ec4,0x3f753ec4,0xbe953f6d,
0xbf22bf55,0x3f46bf0e,0xbf7fbe48,0x3dc9bf7b,0x3f80,0xbf808000,0x3f80,0xbf808000,0xbf80,0x3f808000,0xbf80,0x3f808000,
0x3f80,0xbf808000,0x3f80,0xbf808000,0xbf80,0x3f808000,0xbf80,0x3f808000,0xbdc93f80,0xbf7f8000,0xbf463f35,0xbf22bf35,
0x3e95bf7b,0x3f753e48,0x3f62bf0e,0x3ef13f55,0xbef13f6d,0xbf62bec4,0xbf753ec4,0xbe95bf6d,0x3f22bf55,0x3f463f0e,0x3f7fbe48,0x3dc93f7b,
0xbe483f80,0xbf7b8000,0xbf7b0000,0x3e48bf80,0x3f0ebf6d,0x3f553ec4,0x3f553ec4,0xbf0e3f6d,0xbf553f35,0xbf0ebf35,0xbf0ebf35,0x3f55bf35,
0x3f7bbec4,0x3e483f6d,0x3e483f6d,0xbf7b3ec4,0xbe953f80,0xbf758000,0xbef1bf35,0x3f62bf35,0x3f46bf55,0x3f223f0e,0xbdc93f7b,0xbf7f3e48,
0xbf7f3ec4,0xbdc9bf6d,0x3f22bf6d,0x3f463ec4,0x3f623e48,0xbef13f7b,0xbf753f0e,0xbe95bf55,0xbec43f80,0xbf6d8000,0x3ec4bf80,0x3f6d8000,
0x3f6dbf35,0x3ec43f35,0xbf6d3f35,0xbec4bf35,0xbf6d0000,0x3ec4bf80,0x3f6d0000,0xbec43f80,0x3ec43f35,0xbf6d3f35,0xbec4bf35,0x3f6dbf35,
0xbef13f80,0xbf628000,0x3f75bf35,0x3e953f35,0x3f7fbf0e,0x3dc93f55,0xbf46be48,0x3f22bf7b,0xbf22bec4,0x3f46bf6d,0xbdc93f6d,0xbf7f3ec4,
0xbe953f7b,0xbf753e48,0x3f62bf55,0x3ef13f0e,0xbf0e3f80,0xbf558000,0x3f550000,0xbf0e3f80,0x3f7bbec4,0xbe483f6d,0x3e48bf6d,0x3f7bbec4,
0xbe48bf35,0x3f7bbf35,0xbf7b3f35,0xbe48bf35,0xbf553f6d,0xbf0ebec4,0x3f0e3ec4,0xbf553f6d,0xbf223f80,0xbf468000,0x3dc93f35,0xbf7f3f35,
0x3f62be48,0xbef13f7b,0x3f75bf55,0x3e953f0e,0x3e95bf6d,0x3f75bec4,0xbef1bec4,0x3f62bf6d,0xbf7f3f0e,0x3dc9bf55,0xbf463f7b,0xbf22be48,
0xbf353f80,0xbf358000,0xbf353f80,0xbf358000,0x3f350000,0xbf353f80,0x3f350000,0xbf353f80,0x3f35bf80,0x3f358000,0x3f35bf80,0x3f358000,
0xbf350000,0x3f35bf80,0xbf350000,0x3f35bf80,0xbf463f80,0xbf228000,0xbf7f3f35,0x3dc9bf35,0x3ef13e48,0xbf623f7b,0xbe953f55,0xbf753f0e,
0x3f75bf6d,0x3e953ec4,0x3f62bec4,0xbef13f6d,0xbdc9bf0e,0x3f7fbf55,0x3f22bf7b,0x3f46be48,0xbf553f80,0xbf0e8000,0xbf0e0000,0x3f55bf80,
0x3e483ec4,0xbf7b3f6d,0xbf7b3f6d,0xbe48bec4,0x3f7bbf35,0xbe483f35,0xbe483f35,0xbf7b3f35,0x3f0ebf6d,0x3f55bec4,0x3f55bec4,0xbf0e3f6d,
0xbf623f80,0xbef18000,0x3e95bf35,0x3f75bf35,0xbdc93f0e,0xbf7f3f55,0xbf223e48,0x3f46bf7b,0x3f46bec4,0xbf223f6d,0xbf7f3f6d,0xbdc9bec4,
0x3f75bf7b,0x3e953e48,0xbef13f55,0xbf623f0e,0xbf6d3f80,0xbec48000,0x3f6dbf80,0x3ec48000,0xbec43f35,0xbf6d3f35,0x3ec4bf35,0x3f6dbf35,
0x3ec40000,0xbf6d3f80,0xbec40000,0x3f6dbf80,0x3f6dbf35,0xbec43f35,0xbf6d3f35,0x3ec4bf35,0xbf753f80,0xbe958000,0x3f62bf35,0xbef13f35,
0xbf223f55,0xbf463f0e,0x3f7fbf7b,0x3dc93e48,0xbdc93ec4,0xbf7f3f6d,0x3f46bf6d,0x3f22bec4,0x3ef1be48,0xbf623f7b,0x3e95bf0e,0x3f75bf55,
0xbf7b3f80,0xbe488000,0x3e480000,0xbf7b3f80,0xbf553f6d,0xbf0e3ec4,0x3f0ebec4,0xbf553f6d,0xbf0e3f35,0xbf553f35,0x3f55bf35,0xbf0e3f35,
0xbe483ec4,0xbf7b3f6d,0x3f7bbf6d,0xbe483ec4,0xbf7f3f80,0xbdc98000,0xbf223f35,0xbf463f35,0xbf753f7b,0xbe953e48,0xbef13f0e,0xbf623f55,
0xbf623f6d,0xbef13ec4,0xbe953ec4,0xbf753f6d,0xbf463f55,0xbf223f0e,0xbdc93e48,0xbf7f3f7b,0x3f803f80,0xbf803f80,0x3f803f80,0xbf803f80,
0x3f803f80,0xbf803f80,0x3f803f80,0xbf803f80,0x3f803f80,0xbf803f80,0x3f803f80,0xbf803f80,0x3f803f80,0xbf803f80,0x3f803f80,0xbf803f80,
0xbdc90000,0xbf7fbf80,0xbf46bf35,0xbf22bf35,0xbe95be48,0xbf75bf7b,0xbf62bf55,0xbef1bf0e,0xbef1bec4,0xbf62bf6d,0xbf75bf6d,0xbe95bec4,
0xbf22bf0e,0xbf46bf55,0xbf7fbf7b,0xbdc9be48,0xbf7bbf80,0x3e488000,0x3e480000,0x3f7b3f80,0xbf55bf6d,0x3f0e3ec4,0x3f0e3ec4,0x3f553f6d,
0xbf0ebf35,0x3f553f35,0x3f553f35,0x3f0e3f35,0xbe48bec4,0x3f7b3f6d,0x3f7b3f6d,0x3e483ec4,0x3e950000,0x3f753f80,0x3ef13f35,0xbf62bf35,
0x3f463f0e,0x3f223f55,0xbdc93e48,0xbf7fbf7b,0x3f7f3f6d,0x3dc93ec4,0xbf22bec4,0xbf46bf6d,0x3f623f7b,0xbef1be48,0xbf75bf55,0xbe95bf0e,
0x3f6d3f80,0xbec48000,0xbf6dbf80,0x3ec48000,0x3ec43f35,0xbf6dbf35,0xbec4bf35,0x3f6d3f35,0xbec40000,0xbf6dbf80,0x3ec40000,0x3f6d3f80,
0xbf6dbf35,0xbec4bf35,0x3f6d3f35,0x3ec43f35,0xbef10000,0xbf62bf80,0x3f753f35,0x3e953f35,0xbf7fbf55,0xbdc9bf0e,0x3f463f7b,0xbf22be48,
0xbf22bf6d,0x3f463ec4,0xbdc93ec4,0xbf7fbf6d,0x3e95be48,0x3f753f7b,0xbf62bf0e,0xbef1bf55,0xbf55bf80,0x3f0e8000,0xbf0e0000,0xbf55bf80,
0x3e48bec4,0x3f7b3f6d,0xbf7bbf6d,0x3e48bec4,0x3f7b3f35,0x3e483f35,0xbe48bf35,0x3f7b3f35,0x3f0e3f6d,0xbf55bec4,0x3f553ec4,0x3f0e3f6d,
0x3f220000,0x3f463f80,0xbdc9bf35,0x3f7f3f35,0x3f623f7b,0xbef13e48,0x3f753f0e,0x3e953f55,0xbe953ec4,0xbf75bf6d,0x3ef13f6d,0xbf62bec4,
0xbf7fbf55,0x3dc9bf0e,0xbf46be48,0xbf22bf7b,0x3f353f80,0xbf358000,0x3f353f80,0xbf358000,0xbf350000,0xbf35bf80,0xbf350000,0xbf35bf80,
0xbf35bf80,0x3f358000,0xbf35bf80,0x3f358000,0x3f350000,0x3f353f80,0x3f350000,0x3f353f80,0xbf460000,0xbf22bf80,0xbf7fbf35,0x3dc9bf35,
0xbef1bf7b,0x3f623e48,0x3e95bf0e,0x3f753f55,0x3f753ec4,0x3e953f6d,0x3f623f6d,0xbef13ec4,0x3dc93f55,0xbf7fbf0e,0xbf223e48,0xbf46bf7b,
0xbf0ebf80,0x3f558000,0x3f550000,0x3f0e3f80,0x3f7b3ec4,0x3e483f6d,0x3e483f6d,0xbf7bbec4,0xbe483f35,0xbf7bbf35,0xbf7bbf35,0x3e48bf35,
0xbf55bf6d,0x3f0ebec4,0x3f0ebec4,0x3f553f6d,0x3f620000,0x3ef13f80,0xbe953f35,0xbf75bf35,0xbdc93f55,0xbf7fbf0e,0xbf22bf7b,0x3f46be48,
0xbf46bf6d,0x3f22bec4,0x3f7f3ec4,0x3dc93f6d,0x3f753e48,0x3e953f7b,0xbef13f0e,0xbf62bf55,0x3ec43f80,0xbf6d8000,0xbec4bf80,0x3f6d8000,
0xbf6dbf35,0x3ec4bf35,0x3f6d3f35,0xbec43f35,0x3f6d0000,0x3ec43f80,0xbf6d0000,0xbec4bf80,0xbec43f35,0xbf6dbf35,0x3ec4bf35,0x3f6d3f35,
0xbf750000,0xbe95bf80,0x3f623f35,0xbef13f35,0x3f22bf0e,0x3f463f55,0xbf7fbe48,0xbdc9bf7b,0xbdc93f6d,0xbf7fbec4,0x3f46bec4,0x3f223f6d,
0xbef1bf7b,0x3f62be48,0xbe953f55,0xbf75bf0e,0xbe48bf80,0x3f7b8000,0xbf7b0000,0xbe48bf80,0x3f0e3f6d,0xbf553ec4,0x3f55bec4,0x3f0e3f6d,
0xbf55bf35,0x3f0ebf35,0xbf0e3f35,0xbf55bf35,0x3f7b3ec4,0xbe483f6d,0x3e48bf6d,0x3f7b3ec4,0x3f7f0000,0x3dc93f80,0x3f22bf35,0x3f463f35,
0xbf753e48,0xbe95bf7b,0xbef13f55,0xbf62bf0e,0x3f62bec4,0x3ef13f6d,0x3e95bf6d,0x3f753ec4,0xbf463f0e,0xbf22bf55,0xbdc93f7b,0xbf7fbe48,
0x3f80,0xbf808000,0x3f80,0xbf808000,0xbf80,0x3f808000,0xbf80,0x3f808000,0x3f80,0xbf808000,0x3f80,0xbf808000,
0xbf80,0x3f808000,0xbf80,0x3f808000,0xbf7f0000,0x3dc9bf80,0xbf22bf35,0x3f46bf35,0x3f753e48,0xbe953f7b,0x3ef13f55,0xbf623f0e,
0xbf62bec4,0x3ef1bf6d,0xbe95bf6d,0x3f75bec4,0x3f463f0e,0xbf223f55,0x3dc93f7b,0xbf7f3e48,0x3e48bf80,0x3f7b8000,0x3f7b0000,0xbe483f80,
0xbf0e3f6d,0xbf55bec4,0xbf55bec4,0x3f0ebf6d,0x3f55bf35,0x3f0e3f35,0x3f0e3f35,0xbf553f35,0xbf7b3ec4,0xbe48bf6d,0xbe48bf6d,0x3f7bbec4,
0x3f750000,0xbe953f80,0xbf623f35,0xbef1bf35,0xbf22bf0e,0x3f46bf55,0x3f7fbe48,0xbdc93f7b,0x3dc93f6d,0xbf7f3ec4,0xbf46bec4,0x3f22bf6d,
0x3ef1bf7b,0x3f623e48,0x3e953f55,0xbf753f0e,0xbec43f80,0xbf6d8000,0x3ec4bf80,0x3f6d8000,0x3f6dbf35,0x3ec43f35,0xbf6d3f35,0xbec4bf35,
0xbf6d0000,0x3ec4bf80,0x3f6d0000,0xbec43f80,0x3ec43f35,0xbf6d3f35,0xbec4bf35,0x3f6dbf35,0xbf620000,0x3ef1bf80,0x3e953f35,0xbf753f35,
0x3dc93f55,0xbf7f3f0e,0x3f22bf7b,0x3f463e48,0x3f46bf6d,0x3f223ec4,0xbf7f3ec4,0x3dc9bf6d,0xbf753e48,0x3e95bf7b,0x3ef13f0e,0xbf623f55,
0x3f0ebf80,0x3f558000,0xbf550000,0x3f0ebf80,0xbf7b3ec4,0x3e48bf6d,0xbe483f6d,0xbf7b3ec4,0x3e483f35,0xbf7b3f35,0x3f7bbf35,0x3e483f35,
0x3f55bf6d,0x3f0e3ec4,0xbf0ebec4,0x3f55bf6d,0x3f460000,0xbf223f80,0x3f7fbf35,0x3dc93f35,0x3ef1bf7b,0x3f62be48,0xbe95bf0e,0x3f75bf55,
0xbf753ec4,0x3e95bf6d,0xbf623f6d,0xbef1bec4,0xbdc93f55,0xbf7f3f0e,0x3f223e48,0xbf463f7b,0xbf353f80,0xbf358000,0xbf353f80,0xbf358000,
0x3f350000,0xbf353f80,0x3f350000,0xbf353f80,0x3f35bf80,0x3f358000,0x3f35bf80,0x3f358000,0xbf350000,0x3f35bf80,0xbf350000,0x3f35bf80,
0xbf220000,0x3f46bf80,0x3dc9bf35,0x3f7fbf35,0xbf623f7b,0xbef1be48,0xbf753f0e,0x3e95bf55,0x3e953ec4,0xbf753f6d,0xbef13f6d,0xbf623ec4,
0x3f7fbf55,0x3dc93f0e,0x3f46be48,0xbf223f7b,0x3f55bf80,0x3f0e8000,0x3f0e0000,0xbf553f80,0xbe48bec4,0x3f7bbf6d,0x3f7bbf6d,0x3e483ec4,
0xbf7b3f35,0x3e48bf35,0x3e48bf35,0x3f7bbf35,0xbf0e3f6d,0xbf553ec4,0xbf553ec4,0x3f0ebf6d,0x3ef10000,0xbf623f80,0xbf753f35,0x3e95bf35,
0x3f7fbf55,0xbdc93f0e,0xbf463f7b,0xbf223e48,0x3f22bf6d,0x3f46bec4,0x3dc93ec4,0xbf7f3f6d,0xbe95be48,0x3f75bf7b,0x3f62bf0e,0xbef13f55,
0xbf6d3f80,0xbec48000,0x3f6dbf80,0x3ec48000,0xbec43f35,0xbf6d3f35,0x3ec4bf35,0x3f6dbf35,0x3ec40000,0xbf6d3f80,0xbec40000,0x3f6dbf80,
0x3f6dbf35,0xbec43f35,0xbf6d3f35,0x3ec4bf35,0xbe950000,0x3f75bf80,0xbef13f35,0xbf623f35,0xbf463f0e,0x3f22bf55,0x3dc93e48,0xbf7f3f7b,
0xbf7f3f6d,0x3dc9bec4,0x3f22bec4,0xbf463f6d,0xbf623f7b,0xbef13e48,0x3f75bf55,0xbe953f0e,0x3f7bbf80,0x3e488000,0xbe480000,0x3f7bbf80,
0x3f55bf6d,0x3f0ebec4,0xbf0e3ec4,0x3f55bf6d,0x3f0ebf35,0x3f55bf35,0xbf553f35,0x3f0ebf35,0x3e48bec4,0x3f7bbf6d,0xbf7b3f6d,0x3e48bec4,
0x3dc90000,0xbf7f3f80,0x3f46bf35,0xbf223f35,0x3e95be48,0xbf753f7b,0x3f62bf55,0xbef13f0e,0x3ef1bec4,0xbf623f6d,0x3f75bf6d,0xbe953ec4,
0x3f22bf0e,0xbf463f55,0x3f7fbf7b,0xbdc93e48,0x3f803f80,0xbf803f80,0x3f803f80,0xbf803f80,0x3f803f80,0xbf803f80,0x3f803f80,0xbf803f80,
0x3f803f80,0xbf803f80,0x3f803f80,0xbf803f80,0x3f803f80,0xbf803f80,0x3f803f80,0xbf803f80,0xbf7fbf80,0x3dc98000,0xbf22bf35,0x3f463f35,
0xbf75bf7b,0x3e953e48,0xbef1bf0e,0x3f623f55,0xbf62bf6d,0x3ef13ec4,0xbe95bec4,0x3f753f6d,0xbf46bf55,0x3f223f0e,0xbdc9be48,0x3f7f3f7b,
0x3f7b3f80,0xbe488000,0xbe480000,0xbf7bbf80,0x3f553f6d,0xbf0ebec4,0xbf0ebec4,0xbf55bf6d,0x3f0e3f35,0xbf55bf35,0xbf55bf35,0xbf0ebf35,
0x3e483ec4,0xbf7bbf6d,0xbf7bbf6d,0xbe48bec4,0xbf75bf80,0x3e958000,0x3f623f35,0x3ef13f35,0xbf22bf55,0x3f463f0e,0x3f7f3f7b,0xbdc93e48,
0xbdc9bec4,0x3f7f3f6d,0x3f463f6d,0xbf22bec4,0x3ef13e48,0x3f623f7b,0x3e953f0e,0xbf75bf55,0x3f6d3f80,0xbec48000,0xbf6dbf80,0x3ec48000,
0x3ec43f35,0xbf6dbf35,0xbec4bf35,0x3f6d3f35,0xbec40000,0xbf6dbf80,0x3ec40000,0x3f6d3f80,0xbf6dbf35,0xbec4bf35,0x3f6d3f35,0x3ec43f35,
0xbf62bf80,0x3ef18000,0x3e953f35,0xbf75bf35,0xbdc9bf0e,0x3f7f3f55,0xbf22be48,0xbf46bf7b,0x3f463ec4,0x3f223f6d,0xbf7fbf6d,0x3dc9bec4,
0x3f753f7b,0xbe953e48,0xbef1bf55,0x3f623f0e,0x3f553f80,0xbf0e8000,0x3f0e0000,0x3f553f80,0xbe483ec4,0xbf7bbf6d,0x3f7b3f6d,0xbe483ec4,
0xbf7bbf35,0xbe48bf35,0x3e483f35,0xbf7bbf35,0xbf0ebf6d,0x3f553ec4,0xbf55bec4,0xbf0ebf6d,0xbf46bf80,0x3f228000,0xbf7fbf35,0xbdc9bf35,
0x3ef1be48,0x3f623f7b,0xbe95bf55,0x3f753f0e,0x3f753f6d,0xbe953ec4,0x3f623ec4,0x3ef13f6d,0xbdc93f0e,0xbf7fbf55,0x3f223f7b,0xbf46be48,
0x3f353f80,0xbf358000,0x3f353f80,0xbf358000,0xbf350000,0xbf35bf80,0xbf350000,0xbf35bf80,0xbf35bf80,0x3f358000,0xbf35bf80,0x3f358000,
0x3f350000,0x3f353f80,0x3f350000,0x3f353f80,0xbf22bf80,0x3f468000,0x3dc9bf35,0x3f7f3f35,0x3f623e48,0x3ef13f7b,0x3f753f55,0xbe953f0e,
0x3e953f6d,0xbf75bec4,0xbef13ec4,0xbf62bf6d,0xbf7fbf0e,0xbdc9bf55,0xbf46bf7b,0x3f22be48,0x3f0e3f80,0xbf558000,0xbf550000,0xbf0ebf80,
0xbf7bbec4,0xbe48bf6d,0xbe48bf6d,0x3f7b3ec4,0x3e48bf35,0x3f7b3f35,0x3f7b3f35,0xbe483f35,0x3f553f6d,0xbf0e3ec4,0xbf0e3ec4,0xbf55bf6d,
0xbef1bf80,0x3f628000,0x3f753f35,0xbe953f35,0x3f7f3f0e,0xbdc93f55,0xbf463e48,0xbf22bf7b,0xbf223ec4,0xbf46bf6d,0xbdc9bf6d,0x3f7f3ec4,
0xbe95bf7b,0x3f753e48,0x3f623f55,0xbef13f0e,0x3ec43f80,0xbf6d8000,0xbec4bf80,0x3f6d8000,0xbf6dbf35,0x3ec4bf35,0x3f6d3f35,0xbec43f35,
0x3f6d0000,0x3ec43f80,0xbf6d0000,0xbec4bf80,0xbec43f35,0xbf6dbf35,0x3ec4bf35,0x3f6d3f35,0xbe95bf80,0x3f758000,0xbef13f35,0xbf62bf35,
0x3f463f55,0xbf223f0e,0xbdc9bf7b,0x3f7f3e48,0xbf7fbec4,0x3dc9bf6d,0x3f223f6d,0xbf463ec4,0x3f62be48,0x3ef13f7b,0xbf75bf0e,0x3e95bf55,
0x3e483f80,0xbf7b8000,0x3f7b0000,0x3e483f80,0xbf0ebf6d,0x3f55bec4,0xbf553ec4,0xbf0ebf6d,0x3f553f35,0xbf0e3f35,0x3f0ebf35,0x3f553f35,
0xbf7bbec4,0x3e48bf6d,0xbe483f6d,0xbf7bbec4,0xbdc9bf80,0x3f7f8000,0xbf46bf35,0x3f22bf35,0x3e953f7b,0xbf753e48,0x3f623f0e,0xbef13f55,
0xbef1bf6d,0x3f62bec4,0xbf75bec4,0x3e95bf6d,0x3f223f55,0xbf463f0e,0x3f7f3e48,0xbdc93f7b,0x3f80,0xbf808000,0x3f80,0xbf808000,
0xbf80,0x3f808000,0xbf80,0x3f808000,0x3f80,0xbf808000,0x3f80,0xbf808000,0xbf80,0x3f808000,0xbf80,0x3f808000,
0x3dc9bf80,0x3f7f8000,0x3f46bf35,0x3f223f35,0xbe953f7b,0xbf75be48,0xbf623f0e,0xbef1bf55,0x3ef1bf6d,0x3f623ec4,0x3f75bec4,0x3e953f6d,
0xbf223f55,0xbf46bf0e,0xbf7f3e48,0xbdc9bf7b,0xbe483f80,0xbf7b8000,0xbf7b0000,0x3e48bf80,0x3f0ebf6d,0x3f553ec4,0x3f553ec4,0xbf0e3f6d,
0xbf553f35,0xbf0ebf35,0xbf0ebf35,0x3f55bf35,0x3f7bbec4,0x3e483f6d,0x3e483f6d,0xbf7b3ec4,0x3e95bf80,0x3f758000,0x3ef13f35,0xbf623f35,
0xbf463f55,0xbf22bf0e,0x3dc9bf7b,0x3f7fbe48,0x3f7fbec4,0x3dc93f6d,0xbf223f6d,0xbf46bec4,0xbf62be48,0x3ef1bf7b,0x3f75bf0e,0x3e953f55,
0xbec43f80,0xbf6d8000,0x3ec4bf80,0x3f6d8000,0x3f6dbf35,0x3ec43f35,0xbf6d3f35,0xbec4bf35,0xbf6d0000,0x3ec4bf80,0x3f6d0000,0xbec43f80,
0x3ec43f35,0xbf6d3f35,0xbec4bf35,0x3f6dbf35,0x3ef1bf80,0x3f628000,0xbf753f35,0xbe95bf35,0xbf7f3f0e,0xbdc9bf55,0x3f463e48,0xbf223f7b,
0x3f223ec4,0xbf463f6d,0x3dc9bf6d,0x3f7fbec4,0x3e95bf7b,0x3f75be48,0xbf623f55,0xbef1bf0e,0xbf0e3f80,0xbf558000,0x3f550000,0xbf0e3f80,
0x3f7bbec4,0xbe483f6d,0x3e48bf6d,0x3f7bbec4,0xbe48bf35,0x3f7bbf35,0xbf7b3f35,0xbe48bf35,0xbf553f6d,0xbf0ebec4,0x3f0e3ec4,0xbf553f6d,
0x3f22bf80,0x3f468000,0xbdc9bf35,0x3f7fbf35,0xbf623e48,0x3ef1bf7b,0xbf753f55,0xbe95bf0e,0xbe953f6d,0xbf753ec4,0x3ef13ec4,0xbf623f6d,
0x3f7fbf0e,0xbdc93f55,0x3f46bf7b,0x3f223e48,0xbf353f80,0xbf358000,0xbf353f80,0xbf358000,0x3f350000,0xbf353f80,0x3f350000,0xbf353f80,
0x3f35bf80,0x3f358000,0x3f35bf80,0x3f358000,0xbf350000,0x3f35bf80,0xbf350000,0x3f35bf80,0x3f46bf80,0x3f228000,0x3f7fbf35,0xbdc93f35,
0xbef1be48,0x3f62bf7b,0x3e95bf55,0x3f75bf0e,0xbf753f6d,0xbe95bec4,0xbf623ec4,0x3ef1bf6d,0x3dc93f0e,0xbf7f3f55,0xbf223f7b,0xbf463e48,
0xbf553f80,0xbf0e8000,0xbf0e0000,0x3f55bf80,0x3e483ec4,0xbf7b3f6d,0xbf7b3f6d,0xbe48bec4,0x3f7bbf35,0xbe483f35,0xbe483f35,0xbf7b3f35,
0x3f0ebf6d,0x3f55bec4,0x3f55bec4,0xbf0e3f6d,0x3f62bf80,0x3ef18000,0xbe953f35,0xbf753f35,0x3dc9bf0e,0x3f7fbf55,0x3f22be48,0xbf463f7b,
0xbf463ec4,0x3f22bf6d,0x3f7fbf6d,0x3dc93ec4,0xbf753f7b,0xbe95be48,0x3ef1bf55,0x3f62bf0e,0xbf6d3f80,0xbec48000,0x3f6dbf80,0x3ec48000,
0xbec43f35,0xbf6d3f35,0x3ec4bf35,0x3f6dbf35,0x3ec40000,0xbf6d3f80,0xbec40000,0x3f6dbf80,0x3f6dbf35,0xbec43f35,0xbf6d3f35,0x3ec4bf35,
0x3f75bf80,0x3e958000,0xbf623f35,0x3ef1bf35,0x3f22bf55,0x3f46bf0e,0xbf7f3f7b,0xbdc9be48,0x3dc9bec4,0x3f7fbf6d,0xbf463f6d,0xbf223ec4,
0xbef13e48,0x3f62bf7b,0xbe953f0e,0xbf753f55,0xbf7b3f80,0xbe488000,0x3e480000,0xbf7b3f80,0xbf553f6d,0xbf0e3ec4,0x3f0ebec4,0xbf553f6d,
0xbf0e3f35,0xbf553f35,0x3f55bf35,0xbf0e3f35,0xbe483ec4,0xbf7b3f6d,0x3f7bbf6d,0xbe483ec4,0x3f7fbf80,0x3dc98000,0x3f22bf35,0x3f46bf35,
0x3f75bf7b,0x3e95be48,0x3ef1bf0e,0x3f62bf55,0x3f62bf6d,0x3ef1bec4,0x3e95bec4,0x3f75bf6d,0x3f46bf55,0x3f22bf0e,0x3dc9be48,0x3f7fbf7b,
0x3f803f80,0xbf803f80,0x3f803f80,0xbf803f80,0x3f803f80,0xbf803f80,0x3f803f80,0xbf803f80,0x3f803f80,0xbf803f80,0x3f803f80,0xbf803f80,
0x3f803f80,0xbf803f80,0x3f803f80,0xbf803f80,0x3dc90000,0x3f7f3f80,0x3f463f35,0x3f223f35,0x3e953e48,0x3f753f7b,0x3f623f55,0x3ef13f0e,
0x3ef13ec4,0x3f623f6d,0x3f753f6d,0x3e953ec4,0x3f223f0e,0x3f463f55,0x3f7f3f7b,0x3dc93e48,0xbf7bbf80,0x3e488000,0x3e480000,0x3f7b3f80,
0xbf55bf6d,0x3f0e3ec4,0x3f0e3ec4,0x3f553f6d,0xbf0ebf35,0x3f553f35,0x3f553f35,0x3f0e3f35,0xbe48bec4,0x3f7b3f6d,0x3f7b3f6d,0x3e483ec4,
0xbe950000,0xbf75bf80,0xbef1bf35,0x3f623f35,0xbf46bf0e,0xbf22bf55,0x3dc9be48,0x3f7f3f7b,0xbf7fbf6d,0xbdc9bec4,0x3f223ec4,0x3f463f6d,
0xbf62bf7b,0x3ef13e48,0x3f753f55,0x3e953f0e,0x3f6d3f80,0xbec48000,0xbf6dbf80,0x3ec48000,0x3ec43f35,0xbf6dbf35,0xbec4bf35,0x3f6d3f35,
0xbec40000,0xbf6dbf80,0x3ec40000,0x3f6d3f80,0xbf6dbf35,0xbec4bf35,0x3f6d3f35,0x3ec43f35,0x3ef10000,0x3f623f80,0xbf75bf35,0xbe95bf35,
0x3f7f3f55,0x3dc93f0e,0xbf46bf7b,0x3f223e48,0x3f223f6d,0xbf46bec4,0x3dc9bec4,0x3f7f3f6d,0xbe953e48,0xbf75bf7b,0x3f623f0e,0x3ef13f55,
0xbf55bf80,0x3f0e8000,0xbf0e0000,0xbf55bf80,0x3e48bec4,0x3f7b3f6d,0xbf7bbf6d,0x3e48bec4,0x3f7b3f35,0x3e483f35,0xbe48bf35,0x3f7b3f35,
0x3f0e3f6d,0xbf55bec4,0x3f553ec4,0x3f0e3f6d,0xbf220000,0xbf46bf80,0x3dc93f35,0xbf7fbf35,0xbf62bf7b,0x3ef1be48,0xbf75bf0e,0xbe95bf55,
0x3e95bec4,0x3f753f6d,0xbef1bf6d,0x3f623ec4,0x3f7f3f55,0xbdc93f0e,0x3f463e48,0x3f223f7b,0x3f353f80,0xbf358000,0x3f353f80,0xbf358000,
0xbf350000,0xbf35bf80,0xbf350000,0xbf35bf80,0xbf35bf80,0x3f358000,0xbf35bf80,0x3f358000,0x3f350000,0x3f353f80,0x3f350000,0x3f353f80,
0x3f460000,0x3f223f80,0x3f7f3f35,0xbdc93f35,0x3ef13f7b,0xbf62be48,0xbe953f0e,0xbf75bf55,0xbf75bec4,0xbe95bf6d,0xbf62bf6d,0x3ef1bec4,
0xbdc9bf55,0x3f7f3f0e,0x3f22be48,0x3f463f7b,0xbf0ebf80,0x3f558000,0x3f550000,0x3f0e3f80,0x3f7b3ec4,0x3e483f6d,0x3e483f6d,0xbf7bbec4,
0xbe483f35,0xbf7bbf35,0xbf7bbf35,0x3e48bf35,0xbf55bf6d,0x3f0ebec4,0x3f0ebec4,0x3f553f6d,0xbf620000,0xbef1bf80,0x3e95bf35,0x3f753f35,
0x3dc9bf55,0x3f7f3f0e,0x3f223f7b,0xbf463e48,0x3f463f6d,0xbf223ec4,0xbf7fbec4,0xbdc9bf6d,0xbf75be48,0xbe95bf7b,0x3ef1bf0e,0x3f623f55,
0x3ec43f80,0xbf6d8000,0xbec4bf80,0x3f6d8000,0xbf6dbf35,0x3ec4bf35,0x3f6d3f35,0xbec43f35,0x3f6d0000,0x3ec43f80,0xbf6d0000,0xbec4bf80,
0xbec43f35,0xbf6dbf35,0x3ec4bf35,0x3f6d3f35,0x3f750000,0x3e953f80,0xbf62bf35,0x3ef1bf35,0xbf223f0e,0xbf46bf55,0x3f7f3e48,0x3dc93f7b,
0x3dc9bf6d,0x3f7f3ec4,0xbf463ec4,0xbf22bf6d,0x3ef13f7b,0xbf623e48,0x3e95bf55,0x3f753f0e,0xbe48bf80,0x3f7b8000,0xbf7b0000,0xbe48bf80,
0x3f0e3f6d,0xbf553ec4,0x3f55bec4,0x3f0e3f6d,0xbf55bf35,0x3f0ebf35,0xbf0e3f35,0xbf55bf35,0x3f7b3ec4,0xbe483f6d,0x3e48bf6d,0x3f7b3ec4,
0xbf7f0000,0xbdc9bf80,0xbf223f35,0xbf46bf35,0x3f75be48,0x3e953f7b,0x3ef1bf55,0x3f623f0e,0xbf623ec4,0xbef1bf6d,0xbe953f6d,0xbf75bec4,
0x3f46bf0e,0x3f223f55,0x3dc9bf7b,0x3f7f3e48,0x3f80,0xbf808000,0x3f80,0xbf808000,0xbf80,0x3f808000,0xbf80,0x3f808000,
0x3f80,0xbf808000,0x3f80,0xbf808000,0xbf80,0x3f808000,0xbf80,0x3f808000,0x3f7f0000,0xbdc93f80,0x3f223f35,0xbf463f35,
0xbf75be48,0x3e95bf7b,0xbef1bf55,0x3f62bf0e,0x3f623ec4,0xbef13f6d,0x3e953f6d,0xbf753ec4,0xbf46bf0e,0x3f22bf55,0xbdc9bf7b,0x3f7fbe48,
0x3e48bf80,0x3f7b8000,0x3f7b0000,0xbe483f80,0xbf0e3f6d,0xbf55bec4,0xbf55bec4,0x3f0ebf6d,0x3f55bf35,0x3f0e3f35,0x3f0e3f35,0xbf553f35,
0xbf7b3ec4,0xbe48bf6d,0xbe48bf6d,0x3f7bbec4,0xbf750000,0x3e95bf80,0x3f62bf35,0x3ef13f35,0x3f223f0e,0xbf463f55,0xbf7f3e48,0x3dc9bf7b,
0xbdc9bf6d,0x3f7fbec4,0x3f463ec4,0xbf223f6d,0xbef13f7b,0xbf62be48,0xbe95bf55,0x3f75bf0e,0xbec43f80,0xbf6d8000,0x3ec4bf80,0x3f6d8000,
0x3f6dbf35,0x3ec43f35,0xbf6d3f35,0xbec4bf35,0xbf6d0000,0x3ec4bf80,0x3f6d0000,0xbec43f80,0x3ec43f35,0xbf6d3f35,0xbec4bf35,0x3f6dbf35,
0x3f620000,0xbef13f80,0xbe95bf35,0x3f75bf35,0xbdc9bf55,0x3f7fbf0e,0xbf223f7b,0xbf46be48,0xbf463f6d,0xbf22bec4,0x3f7fbec4,0xbdc93f6d,
0x3f75be48,0xbe953f7b,0xbef1bf0e,0x3f62bf55,0x3f0ebf80,0x3f558000,0xbf550000,0x3f0ebf80,0xbf7b3ec4,0x3e48bf6d,0xbe483f6d,0xbf7b3ec4,
0x3e483f35,0xbf7b3f35,0x3f7bbf35,0x3e483f35,0x3f55bf6d,0x3f0e3ec4,0xbf0ebec4,0x3f55bf6d,0xbf460000,0x3f22bf80,0xbf7f3f35,0xbdc9bf35,
0xbef13f7b,0xbf623e48,0x3e953f0e,0xbf753f55,0x3f75bec4,0xbe953f6d,0x3f62bf6d,0x3ef13ec4,0x3dc9bf55,0x3f7fbf0e,0xbf22be48,0x3f46bf7b,
0xbf353f80,0xbf358000,0xbf353f80,0xbf358000,0x3f350000,0xbf353f80,0x3f350000,0xbf353f80,0x3f35bf80,0x3f358000,0x3f35bf80,0x3f358000,
0xbf350000,0x3f35bf80,0xbf350000,0x3f35bf80,0x3f220000,0xbf463f80,0xbdc93f35,0xbf7f3f35,0x3f62bf7b,0x3ef13e48,0x3f75bf0e,0xbe953f55,
0xbe95bec4,0x3f75bf6d,0x3ef1bf6d,0x3f62bec4,0xbf7f3f55,0xbdc9bf0e,0xbf463e48,0x3f22bf7b,0x3f55bf80,0x3f0e8000,0x3f0e0000,0xbf553f80,
0xbe48bec4,0x3f7bbf6d,0x3f7bbf6d,0x3e483ec4,0xbf7b3f35,0x3e48bf35,0x3e48bf35,0x3f7bbf35,0xbf0e3f6d,0xbf553ec4,0xbf553ec4,0x3f0ebf6d,
0xbef10000,0x3f62bf80,0x3f75bf35,0xbe953f35,0xbf7f3f55,0x3dc9bf0e,0x3f46bf7b,0x3f22be48,0xbf223f6d,0xbf463ec4,0xbdc9bec4,0x3f7fbf6d,
0x3e953e48,0xbf753f7b,0xbf623f0e,0x3ef1bf55,0xbf6d3f80,0xbec48000,0x3f6dbf80,0x3ec48000,0xbec43f35,0xbf6d3f35,0x3ec4bf35,0x3f6dbf35,
0x3ec40000,0xbf6d3f80,0xbec40000,0x3f6dbf80,0x3f6dbf35,0xbec43f35,0xbf6d3f35,0x3ec4bf35,0x3e950000,0xbf753f80,0x3ef1bf35,0x3f62bf35,
0x3f46bf0e,0xbf223f55,0xbdc9be48,0x3f7fbf7b,0x3f7fbf6d,0xbdc93ec4,0xbf223ec4,0x3f46bf6d,0x3f62bf7b,0x3ef1be48,0xbf753f55,0x3e95bf0e,
0x3f7bbf80,0x3e488000,0xbe480000,0x3f7bbf80,0x3f55bf6d,0x3f0ebec4,0xbf0e3ec4,0x3f55bf6d,0x3f0ebf35,0x3f55bf35,0xbf553f35,0x3f0ebf35,
0x3e48bec4,0x3f7bbf6d,0xbf7b3f6d,0x3e48bec4,0xbdc90000,0x3f7fbf80,0xbf463f35,0x3f22bf35,0xbe953e48,0x3f75bf7b,0xbf623f55,0x3ef1bf0e,
0xbef13ec4,0x3f62bf6d,0xbf753f6d,0x3e95bec4,0xbf223f0e,0x3f46bf55,0xbf7f3f7b,0x3dc9be48,0x3f803f80,0x3f803f80,0x3f803f80,0x3f803f80,
0x3f803f80,0x3f803f80,0x3f803f80,0x3f803f80,0x3f803f80,0x3f803f80,0x3f803f80,0x3f803f80,0x3f803f80,0x3f803f80,0x3f803f80,0x3f803f80,
0x0,0x0,0x0,0x0,0x0,0x0,0x0,0x0,0x0,0x0,0x0,0x0,
0x0,0x0,0x0,0x0,0xbe480000,0xbf0ebec4,0xbf55bf35,0xbf7bbf6d,0x3f7b3f80,0x3f553f6d,0x3f0e3f35,0x3e483ec4,
0x3e480000,0x3f0e3ec4,0x3f553f35,0x3f7b3f6d,0xbf7bbf80,0xbf55bf6d,0xbf0ebf35,0xbe48bec4,0x3f7b3f80,0x3f553f6d,0x3f0e3f35,0x3e483ec4,
0x3e480000,0x3f0e3ec4,0x3f553f35,0x3f7b3f6d,0xbf7bbf80,0xbf55bf6d,0xbf0ebf35,0xbe48bec4,0xbe480000,0xbf0ebec4,0xbf55bf35,0xbf7bbf6d,
0x3f6d3f80,0x3ec43f35,0xbec40000,0xbf6dbf35,0xbf6dbf80,0xbec4bf35,0x3ec40000,0x3f6d3f35,0x3f6d3f80,0x3ec43f35,0xbec40000,0xbf6dbf35,
0xbf6dbf80,0xbec4bf35,0x3ec40000,0x3f6d3f35,0x3ec40000,0x3f6d3f35,0x3f6d3f80,0x3ec43f35,0xbec40000,0xbf6dbf35,0xbf6dbf80,0xbec4bf35,
0x3ec40000,0x3f6d3f35,0x3f6d3f80,0x3ec43f35,0xbec40000,0xbf6dbf35,0xbf6dbf80,0xbec4bf35,0xbf0e0000,0xbf7bbf6d,0xbe48bf35,0x3f553ec4,
0xbf55bf80,0x3e48bec4,0x3f7b3f35,0x3f0e3f6d,0x3f0e0000,0x3f7b3f6d,0x3e483f35,0xbf55bec4,0x3f553f80,0xbe483ec4,0xbf7bbf35,0xbf0ebf6d,
0x3f553f80,0xbe483ec4,0xbf7bbf35,0xbf0ebf6d,0xbf0e0000,0xbf7bbf6d,0xbe48bf35,0x3f553ec4,0xbf55bf80,0x3e48bec4,0x3f7b3f35,0x3f0e3f6d,
0x3f0e0000,0x3f7b3f6d,0x3e483f35,0xbf55bec4,0x3f350000,0x3f353f80,0xbf350000,0xbf35bf80,0x3f350000,0x3f353f80,0xbf350000,0xbf35bf80,
0x3f350000,0x3f353f80,0xbf350000,0xbf35bf80,0x3f350000,0x3f353f80,0xbf350000,0xbf35bf80,0x3f353f80,0xbf350000,0xbf35bf80,0x3f350000,
0x3f353f80,0xbf350000,0xbf35bf80,0x3f350000,0x3f353f80,0xbf350000,0xbf35bf80,0x3f350000,0x3f353f80,0xbf350000,0xbf35bf80,0x3f350000,
0x3f0e3f80,0xbf7bbec4,0x3e48bf35,0x3f553f6d,0x3f550000,0x3e483f6d,0xbf7bbf35,0x3f0ebec4,0xbf0ebf80,0x3f7b3ec4,0xbe483f35,0xbf55bf6d,
0xbf550000,0xbe48bf6d,0x3f7b3f35,0xbf0e3ec4,0xbf550000,0xbe48bf6d,0x3f7b3f35,0xbf0e3ec4,0x3f0e3f80,0xbf7bbec4,0x3e48bf35,0x3f553f6d,
0x3f550000,0x3e483f6d,0xbf7bbf35,0x3f0ebec4,0xbf0ebf80,0x3f7b3ec4,0xbe483f35,0xbf55bf6d,0x3f6d0000,0xbec43f35,0xbec4bf80,0x3f6d3f35,
0xbf6d0000,0x3ec4bf35,0x3ec43f80,0xbf6dbf35,0x3f6d0000,0xbec43f35,0xbec4bf80,0x3f6d3f35,0xbf6d0000,0x3ec4bf35,0x3ec43f80,0xbf6dbf35,
0x3ec43f80,0xbf6dbf35,0x3f6d0000,0xbec43f35,0xbec4bf80,0x3f6d3f35,0xbf6d0000,0x3ec4bf35,0x3ec43f80,0xbf6dbf35,0x3f6d0000,0xbec43f35,
0xbec4bf80,0x3f6d3f35,0xbf6d0000,0x3ec4bf35,0x3e483f80,0xbf0ebf6d,0x3f553f35,0xbf7bbec4,0xbf7b0000,0x3f55bec4,0xbf0e3f35,0x3e48bf6d,
0xbe48bf80,0x3f0e3f6d,0xbf55bf35,0x3f7b3ec4,0x3f7b0000,0xbf553ec4,0x3f0ebf35,0xbe483f6d,0xbf7b0000,0x3f55bec4,0xbf0e3f35,0x3e48bf6d,
0xbe48bf80,0x3f0e3f6d,0xbf55bf35,0x3f7b3ec4,0x3f7b0000,0xbf553ec4,0x3f0ebf35,0xbe483f6d,0x3e483f80,0xbf0ebf6d,0x3f553f35,0xbf7bbec4,
0x3f80,0xbf80,0x3f80,0xbf80,0x3f80,0xbf80,0x3f80,0xbf80,0x3f80,0xbf80,0x3f80,0xbf80,
0x3f80,0xbf80,0x3f80,0xbf80,0x3f800000,0xbf800000,0x3f800000,0xbf800000,0x3f800000,0xbf800000,0x3f800000,0xbf800000,
0x3f800000,0xbf800000,0x3f800000,0xbf800000,0x3f800000,0xbf800000,0x3f800000,0xbf800000,0xbf7b0000,0x3f553ec4,0xbf0ebf35,0x3e483f6d,
0xbe483f80,0x3f0ebf6d,0xbf553f35,0x3f7bbec4,0x3f7b0000,0xbf55bec4,0x3f0e3f35,0xbe48bf6d,0x3e48bf80,0xbf0e3f6d,0x3f55bf35,0xbf7b3ec4,
0xbe483f80,0x3f0ebf6d,0xbf553f35,0x3f7bbec4,0x3f7b0000,0xbf55bec4,0x3f0e3f35,0xbe48bf6d,0x3e48bf80,0xbf0e3f6d,0x3f55bf35,0xbf7b3ec4,
0xbf7b0000,0x3f553ec4,0xbf0ebf35,0x3e483f6d,0xbec43f80,0x3f6dbf35,0xbf6d0000,0x3ec43f35,0x3ec4bf80,0xbf6d3f35,0x3f6d0000,0xbec4bf35,
0xbec43f80,0x3f6dbf35,0xbf6d0000,0x3ec43f35,0x3ec4bf80,0xbf6d3f35,0x3f6d0000,0xbec4bf35,0x3f6d0000,0xbec4bf35,0xbec43f80,0x3f6dbf35,
0xbf6d0000,0x3ec43f35,0x3ec4bf80,0xbf6d3f35,0x3f6d0000,0xbec4bf35,0xbec43f80,0x3f6dbf35,0xbf6d0000,0x3ec43f35,0x3ec4bf80,0xbf6d3f35,
0xbf550000,0xbe483f6d,0x3f7bbf35,0xbf0ebec4,0x3f0ebf80,0xbf7b3ec4,0x3e483f35,0x3f55bf6d,0x3f550000,0x3e48bf6d,0xbf7b3f35,0x3f0e3ec4,
0xbf0e3f80,0x3f7bbec4,0xbe48bf35,0xbf553f6d,0xbf0e3f80,0x3f7bbec4,0xbe48bf35,0xbf553f6d,0xbf550000,0xbe483f6d,0x3f7bbf35,0xbf0ebec4,
0x3f0ebf80,0xbf7b3ec4,0x3e483f35,0x3f55bf6d,0x3f550000,0x3e48bf6d,0xbf7b3f35,0x3f0e3ec4,0x3f350000,0x3f35bf80,0xbf350000,0xbf353f80,
0x3f350000,0x3f35bf80,0xbf350000,0xbf353f80,0x3f350000,0x3f35bf80,0xbf350000,0xbf353f80,0x3f350000,0x3f35bf80,0xbf350000,0xbf353f80,
0xbf353f80,0x3f350000,0x3f35bf80,0xbf350000,0xbf353f80,0x3f350000,0x3f35bf80,0xbf350000,0xbf353f80,0x3f350000,0x3f35bf80,0xbf350000,
0xbf353f80,0x3f350000,0x3f35bf80,0xbf350000,0xbf553f80,0x3e483ec4,0x3f7bbf35,0x3f0ebf6d,0x3f0e0000,0x3f7bbf6d,0x3e48bf35,0xbf553ec4,
0x3f55bf80,0xbe48bec4,0xbf7b3f35,0xbf0e3f6d,0xbf0e0000,0xbf7b3f6d,0xbe483f35,0x3f55bec4,0xbf0e0000,0xbf7b3f6d,0xbe483f35,0x3f55bec4,
0xbf553f80,0x3e483ec4,0x3f7bbf35,0x3f0ebf6d,0x3f0e0000,0x3f7bbf6d,0x3e48bf35,0xbf553ec4,0x3f55bf80,0xbe48bec4,0xbf7b3f35,0xbf0e3f6d,
0x3ec40000,0x3f6dbf35,0x3f6dbf80,0x3ec4bf35,0xbec40000,0xbf6d3f35,0xbf6d3f80,0xbec43f35,0x3ec40000,0x3f6dbf35,0x3f6dbf80,0x3ec4bf35,
0xbec40000,0xbf6d3f35,0xbf6d3f80,0xbec43f35,0xbf6d3f80,0xbec43f35,0x3ec40000,0x3f6dbf35,0x3f6dbf80,0x3ec4bf35,0xbec40000,0xbf6d3f35,
0xbf6d3f80,0xbec43f35,0x3ec40000,0x3f6dbf35,0x3f6dbf80,0x3ec4bf35,0xbec40000,0xbf6d3f35,0xbf7b3f80,0xbf553f6d,0xbf0e3f35,0xbe483ec4,
0xbe480000,0xbf0e3ec4,0xbf553f35,0xbf7b3f6d,0x3f7bbf80,0x3f55bf6d,0x3f0ebf35,0x3e48bec4,0x3e480000,0x3f0ebec4,0x3f55bf35,0x3f7bbf6d,
0xbe480000,0xbf0e3ec4,0xbf553f35,0xbf7b3f6d,0x3f7bbf80,0x3f55bf6d,0x3f0ebf35,0x3e48bec4,0x3e480000,0x3f0ebec4,0x3f55bf35,0x3f7bbf6d,
0xbf7b3f80,0xbf553f6d,0xbf0e3f35,0xbe483ec4,0xbf803f80,0xbf803f80,0xbf803f80,0xbf803f80,0xbf803f80,0xbf803f80,0xbf803f80,0xbf803f80,
0xbf803f80,0xbf803f80,0xbf803f80,0xbf803f80,0xbf803f80,0xbf803f80,0xbf803f80,0xbf803f80,0x0,0x0,0x0,0x0,
0x0,0x0,0x0,0x0,0x0,0x0,0x0,0x0,0x0,0x0,0x0,0x0,
0x3e480000,0x3f0ebec4,0x3f55bf35,0x3f7bbf6d,0xbf7b3f80,0xbf553f6d,0xbf0e3f35,0xbe483ec4,0xbe480000,0xbf0e3ec4,0xbf553f35,0xbf7b3f6d,
0x3f7bbf80,0x3f55bf6d,0x3f0ebf35,0x3e48bec4,0xbf7b3f80,0xbf553f6d,0xbf0e3f35,0xbe483ec4,0xbe480000,0xbf0e3ec4,0xbf553f35,0xbf7b3f6d,
0x3f7bbf80,0x3f55bf6d,0x3f0ebf35,0x3e48bec4,0x3e480000,0x3f0ebec4,0x3f55bf35,0x3f7bbf6d,0xbf6d3f80,0xbec43f35,0x3ec40000,0x3f6dbf35,
0x3f6dbf80,0x3ec4bf35,0xbec40000,0xbf6d3f35,0xbf6d3f80,0xbec43f35,0x3ec40000,0x3f6dbf35,0x3f6dbf80,0x3ec4bf35,0xbec40000,0xbf6d3f35,
0xbec40000,0xbf6d3f35,0xbf6d3f80,0xbec43f35,0x3ec40000,0x3f6dbf35,0x3f6dbf80,0x3ec4bf35,0xbec40000,0xbf6d3f35,0xbf6d3f80,0xbec43f35,
0x3ec40000,0x3f6dbf35,0x3f6dbf80,0x3ec4bf35,0x3f0e0000,0x3f7bbf6d,0x3e48bf35,0xbf553ec4,0x3f55bf80,0xbe48bec4,0xbf7b3f35,0xbf0e3f6d,
0xbf0e0000,0xbf7b3f6d,0xbe483f35,0x3f55bec4,0xbf553f80,0x3e483ec4,0x3f7bbf35,0x3f0ebf6d,0xbf553f80,0x3e483ec4,0x3f7bbf35,0x3f0ebf6d,
0x3f0e0000,0x3f7bbf6d,0x3e48bf35,0xbf553ec4,0x3f55bf80,0xbe48bec4,0xbf7b3f35,0xbf0e3f6d,0xbf0e0000,0xbf7b3f6d,0xbe483f35,0x3f55bec4,
0xbf350000,0xbf353f80,0x3f350000,0x3f35bf80,0xbf350000,0xbf353f80,0x3f350000,0x3f35bf80,0xbf350000,0xbf353f80,0x3f350000,0x3f35bf80,
0xbf350000,0xbf353f80,0x3f350000,0x3f35bf80,0xbf353f80,0x3f350000,0x3f35bf80,0xbf350000,0xbf353f80,0x3f350000,0x3f35bf80,0xbf350000,
0xbf353f80,0x3f350000,0x3f35bf80,0xbf350000,0xbf353f80,0x3f350000,0x3f35bf80,0xbf350000,0xbf0e3f80,0x3f7bbec4,0xbe48bf35,0xbf553f6d,
0xbf550000,0xbe483f6d,0x3f7bbf35,0xbf0ebec4,0x3f0ebf80,0xbf7b3ec4,0x3e483f35,0x3f55bf6d,0x3f550000,0x3e48bf6d,0xbf7b3f35,0x3f0e3ec4,
0x3f550000,0x3e48bf6d,0xbf7b3f35,0x3f0e3ec4,0xbf0e3f80,0x3f7bbec4,0xbe48bf35,0xbf553f6d,0xbf550000,0xbe483f6d,0x3f7bbf35,0xbf0ebec4,
0x3f0ebf80,0xbf7b3ec4,0x3e483f35,0x3f55bf6d,0xbf6d0000,0x3ec43f35,0x3ec4bf80,0xbf6d3f35,0x3f6d0000,0xbec4bf35,0xbec43f80,0x3f6dbf35,
0xbf6d0000,0x3ec43f35,0x3ec4bf80,0xbf6d3f35,0x3f6d0000,0xbec4bf35,0xbec43f80,0x3f6dbf35,0xbec43f80,0x3f6dbf35,0xbf6d0000,0x3ec43f35,
0x3ec4bf80,0xbf6d3f35,0x3f6d0000,0xbec4bf35,0xbec43f80,0x3f6dbf35,0xbf6d0000,0x3ec43f35,0x3ec4bf80,0xbf6d3f35,0x3f6d0000,0xbec4bf35,
0xbe483f80,0x3f0ebf6d,0xbf553f35,0x3f7bbec4,0x3f7b0000,0xbf55bec4,0x3f0e3f35,0xbe48bf6d,0x3e48bf80,0xbf0e3f6d,0x3f55bf35,0xbf7b3ec4,
0xbf7b0000,0x3f553ec4,0xbf0ebf35,0x3e483f6d,0x3f7b0000,0xbf55bec4,0x3f0e3f35,0xbe48bf6d,0x3e48bf80,0xbf0e3f6d,0x3f55bf35,0xbf7b3ec4,
0xbf7b0000,0x3f553ec4,0xbf0ebf35,0x3e483f6d,0xbe483f80,0x3f0ebf6d,0xbf553f35,0x3f7bbec4,0x3f80,0xbf80,0x3f80,0xbf80,
0x3f80,0xbf80,0x3f80,0xbf80,0x3f80,0xbf80,0x3f80,0xbf80,0x3f80,0xbf80,0x3f80,0xbf80,
0xbf800000,0x3f800000,0xbf800000,0x3f800000,0xbf800000,0x3f800000,0xbf800000,0x3f800000,0xbf800000,0x3f800000,0xbf800000,0x3f800000,
0xbf800000,0x3f800000,0xbf800000,0x3f800000,0x3f7b0000,0xbf553ec4,0x3f0ebf35,0xbe483f6d,0x3e483f80,0xbf0ebf6d,0x3f553f35,0xbf7bbec4,
0xbf7b0000,0x3f55bec4,0xbf0e3f35,0x3e48bf6d,0xbe48bf80,0x3f0e3f6d,0xbf55bf35,0x3f7b3ec4,0x3e483f80,0xbf0ebf6d,0x3f553f35,0xbf7bbec4,
0xbf7b0000,0x3f55bec4,0xbf0e3f35,0x3e48bf6d,0xbe48bf80,0x3f0e3f6d,0xbf55bf35,0x3f7b3ec4,0x3f7b0000,0xbf553ec4,0x3f0ebf35,0xbe483f6d,
0x3ec43f80,0xbf6dbf35,0x3f6d0000,0xbec43f35,0xbec4bf80,0x3f6d3f35,0xbf6d0000,0x3ec4bf35,0x3ec43f80,0xbf6dbf35,0x3f6d0000,0xbec43f35,
0xbec4bf80,0x3f6d3f35,0xbf6d0000,0x3ec4bf35,0xbf6d0000,0x3ec4bf35,0x3ec43f80,0xbf6dbf35,0x3f6d0000,0xbec43f35,0xbec4bf80,0x3f6d3f35,
0xbf6d0000,0x3ec4bf35,0x3ec43f80,0xbf6dbf35,0x3f6d0000,0xbec43f35,0xbec4bf80,0x3f6d3f35,0x3f550000,0x3e483f6d,0xbf7bbf35,0x3f0ebec4,
0xbf0ebf80,0x3f7b3ec4,0xbe483f35,0xbf55bf6d,0xbf550000,0xbe48bf6d,0x3f7b3f35,0xbf0e3ec4,0x3f0e3f80,0xbf7bbec4,0x3e48bf35,0x3f553f6d,
0x3f0e3f80,0xbf7bbec4,0x3e48bf35,0x3f553f6d,0x3f550000,0x3e483f6d,0xbf7bbf35,0x3f0ebec4,0xbf0ebf80,0x3f7b3ec4,0xbe483f35,0xbf55bf6d,
0xbf550000,0xbe48bf6d,0x3f7b3f35,0xbf0e3ec4,0xbf350000,0xbf35bf80,0x3f350000,0x3f353f80,0xbf350000,0xbf35bf80,0x3f350000,0x3f353f80,
0xbf350000,0xbf35bf80,0x3f350000,0x3f353f80,0xbf350000,0xbf35bf80,0x3f350000,0x3f353f80,0x3f353f80,0xbf350000,0xbf35bf80,0x3f350000,
0x3f353f80,0xbf350000,0xbf35bf80,0x3f350000,0x3f353f80,0xbf350000,0xbf35bf80,0x3f350000,0x3f353f80,0xbf350000,0xbf35bf80,0x3f350000,
0x3f553f80,0xbe483ec4,0xbf7bbf35,0xbf0ebf6d,0xbf0e0000,0xbf7bbf6d,0xbe48bf35,0x3f553ec4,0xbf55bf80,0x3e48bec4,0x3f7b3f35,0x3f0e3f6d,
0x3f0e0000,0x3f7b3f6d,0x3e483f35,0xbf55bec4,0x3f0e0000,0x3f7b3f6d,0x3e483f35,0xbf55bec4,0x3f553f80,0xbe483ec4,0xbf7bbf35,0xbf0ebf6d,
0xbf0e0000,0xbf7bbf6d,0xbe48bf35,0x3f553ec4,0xbf55bf80,0x3e48bec4,0x3f7b3f35,0x3f0e3f6d,0xbec40000,0xbf6dbf35,0xbf6dbf80,0xbec4bf35,
0x3ec40000,0x3f6d3f35,0x3f6d3f80,0x3ec43f35,0xbec40000,0xbf6dbf35,0xbf6dbf80,0xbec4bf35,0x3ec40000,0x3f6d3f35,0x3f6d3f80,0x3ec43f35,
0x3f6d3f80,0x3ec43f35,0xbec40000,0xbf6dbf35,0xbf6dbf80,0xbec4bf35,0x3ec40000,0x3f6d3f35,0x3f6d3f80,0x3ec43f35,0xbec40000,0xbf6dbf35,
0xbf6dbf80,0xbec4bf35,0x3ec40000,0x3f6d3f35,0x3f7b3f80,0x3f553f6d,0x3f0e3f35,0x3e483ec4,0x3e480000,0x3f0e3ec4,0x3f553f35,0x3f7b3f6d,
0xbf7bbf80,0xbf55bf6d,0xbf0ebf35,0xbe48bec4,0xbe480000,0xbf0ebec4,0xbf55bf35,0xbf7bbf6d,0x3e480000,0x3f0e3ec4,0x3f553f35,0x3f7b3f6d,
0xbf7bbf80,0xbf55bf6d,0xbf0ebf35,0xbe48bec4,0xbe480000,0xbf0ebec4,0xbf55bf35,0xbf7bbf6d,0x3f7b3f80,0x3f553f6d,0x3f0e3f35,0x3e483ec4,
0x80008000,0x80008000,0x80008000,0x80008000,0x80008000,0x80008000,0x80008000,0x80008000,0x80008000,0x80008000,0x80008000,0x80008000,
0x80008000,0x80008000,0x80008000,0x80008000,0x3f803f80,0x3f803f80,0x3f803f80,0x3f803f80,0x3f803f80,0x3f803f80,0x3f803f80,0x3f803f80,
0x3f803f80,0x3f803f80,0x3f803f80,0x3f803f80,0x3f803f80,0x3f803f80,0x3f803f80,0x3f803f80,0xbf7bbf80,0xbf55bf6d,0xbf0ebf35,0xbe48bec4,
0xbe488000,0xbf0ebec4,0xbf55bf35,0xbf7bbf6d,0x3f7b3f80,0x3f553f6d,0x3f0e3f35,0x3e483ec4,0x3e488000,0x3f0e3ec4,0x3f553f35,0x3f7b3f6d,
0xbe480000,0xbf0ebec4,0xbf55bf35,0xbf7bbf6d,0x3f7b3f80,0x3f553f6d,0x3f0e3f35,0x3e483ec4,0x3e480000,0x3f0e3ec4,0x3f553f35,0x3f7b3f6d,
0xbf7bbf80,0xbf55bf6d,0xbf0ebf35,0xbe48bec4,0xbec48000,0xbf6dbf35,0xbf6dbf80,0xbec4bf35,0x3ec48000,0x3f6d3f35,0x3f6d3f80,0x3ec43f35,
0xbec48000,0xbf6dbf35,0xbf6dbf80,0xbec4bf35,0x3ec48000,0x3f6d3f35,0x3f6d3f80,0x3ec43f35,0x3f6d3f80,0x3ec43f35,0xbec40000,0xbf6dbf35,
0xbf6dbf80,0xbec4bf35,0x3ec40000,0x3f6d3f35,0x3f6d3f80,0x3ec43f35,0xbec40000,0xbf6dbf35,0xbf6dbf80,0xbec4bf35,0x3ec40000,0x3f6d3f35,
0xbf55bf80,0x3e48bec4,0x3f7b3f35,0x3f0e3f6d,0x3f0e8000,0x3f7b3f6d,0x3e483f35,0xbf55bec4,0x3f553f80,0xbe483ec4,0xbf7bbf35,0xbf0ebf6d,
0xbf0e8000,0xbf7bbf6d,0xbe48bf35,0x3f553ec4,0xbf0e0000,0xbf7bbf6d,0xbe48bf35,0x3f553ec4,0xbf55bf80,0x3e48bec4,0x3f7b3f35,0x3f0e3f6d,
0x3f0e0000,0x3f7b3f6d,0x3e483f35,0xbf55bec4,0x3f553f80,0xbe483ec4,0xbf7bbf35,0xbf0ebf6d,0x3f353f80,0xbf350000,0xbf35bf80,0x3f350000,
0x3f353f80,0xbf350000,0xbf35bf80,0x3f350000,0x3f353f80,0xbf350000,0xbf35bf80,0x3f350000,0x3f353f80,0xbf350000,0xbf35bf80,0x3f350000,
0xbf358000,0xbf35bf80,0x3f358000,0x3f353f80,0xbf358000,0xbf35bf80,0x3f358000,0x3f353f80,0xbf358000,0xbf35bf80,0x3f358000,0x3f353f80,
0xbf358000,0xbf35bf80,0x3f358000,0x3f353f80,0xbf550000,0xbe48bf6d,0x3f7b3f35,0xbf0e3ec4,0x3f0e3f80,0xbf7bbec4,0x3e48bf35,0x3f553f6d,
0x3f550000,0x3e483f6d,0xbf7bbf35,0x3f0ebec4,0xbf0ebf80,0x3f7b3ec4,0xbe483f35,0xbf55bf6d,0xbf0ebf80,0x3f7b3ec4,0xbe483f35,0xbf55bf6d,
0xbf558000,0xbe48bf6d,0x3f7b3f35,0xbf0e3ec4,0x3f0e3f80,0xbf7bbec4,0x3e48bf35,0x3f553f6d,0x3f558000,0x3e483f6d,0xbf7bbf35,0x3f0ebec4,
0x3ec43f80,0xbf6dbf35,0x3f6d0000,0xbec43f35,0xbec4bf80,0x3f6d3f35,0xbf6d0000,0x3ec4bf35,0x3ec43f80,0xbf6dbf35,0x3f6d0000,0xbec43f35,
0xbec4bf80,0x3f6d3f35,0xbf6d0000,0x3ec4bf35,0xbf6d8000,0x3ec4bf35,0x3ec43f80,0xbf6dbf35,0x3f6d8000,0xbec43f35,0xbec4bf80,0x3f6d3f35,
0xbf6d8000,0x3ec4bf35,0x3ec43f80,0xbf6dbf35,0x3f6d8000,0xbec43f35,0xbec4bf80,0x3f6d3f35,0xbf7b0000,0x3f55bec4,0xbf0e3f35,0x3e48bf6d,
0xbe48bf80,0x3f0e3f6d,0xbf55bf35,0x3f7b3ec4,0x3f7b0000,0xbf553ec4,0x3f0ebf35,0xbe483f6d,0x3e483f80,0xbf0ebf6d,0x3f553f35,0xbf7bbec4,
0xbe48bf80,0x3f0e3f6d,0xbf55bf35,0x3f7b3ec4,0x3f7b8000,0xbf553ec4,0x3f0ebf35,0xbe483f6d,0x3e483f80,0xbf0ebf6d,0x3f553f35,0xbf7bbec4,
0xbf7b8000,0x3f55bec4,0xbf0e3f35,0x3e48bf6d,0xbf808000,0x3f808000,0xbf808000,0x3f808000,0xbf808000,0x3f808000,0xbf808000,0x3f808000,
0xbf808000,0x3f808000,0xbf808000,0x3f808000,0xbf808000,0x3f808000,0xbf808000,0x3f808000,0x3f80,0xbf80,0x3f80,0xbf80,
0x3f80,0xbf80,0x3f80,0xbf80,0x3f80,0xbf80,0x3f80,0xbf80,0x3f80,0xbf80,0x3f80,0xbf80,
0x3e48bf80,0xbf0e3f6d,0x3f55bf35,0xbf7b3ec4,0xbf7b8000,0x3f553ec4,0xbf0ebf35,0x3e483f6d,0xbe483f80,0x3f0ebf6d,0xbf553f35,0x3f7bbec4,
0x3f7b8000,0xbf55bec4,0x3f0e3f35,0xbe48bf6d,0xbf7b0000,0x3f553ec4,0xbf0ebf35,0x3e483f6d,0xbe483f80,0x3f0ebf6d,0xbf553f35,0x3f7bbec4,
0x3f7b0000,0xbf55bec4,0x3f0e3f35,0xbe48bf6d,0x3e48bf80,0xbf0e3f6d,0x3f55bf35,0xbf7b3ec4,0xbf6d8000,0x3ec43f35,0x3ec4bf80,0xbf6d3f35,
0x3f6d8000,0xbec4bf35,0xbec43f80,0x3f6dbf35,0xbf6d8000,0x3ec43f35,0x3ec4bf80,0xbf6d3f35,0x3f6d8000,0xbec4bf35,0xbec43f80,0x3f6dbf35,
0xbec43f80,0x3f6dbf35,0xbf6d0000,0x3ec43f35,0x3ec4bf80,0xbf6d3f35,0x3f6d0000,0xbec4bf35,0xbec43f80,0x3f6dbf35,0xbf6d0000,0x3ec43f35,
0x3ec4bf80,0xbf6d3f35,0x3f6d0000,0xbec4bf35,0x3f0ebf80,0xbf7b3ec4,0x3e483f35,0x3f55bf6d,0x3f558000,0x3e48bf6d,0xbf7b3f35,0x3f0e3ec4,
0xbf0e3f80,0x3f7bbec4,0xbe48bf35,0xbf553f6d,0xbf558000,0xbe483f6d,0x3f7bbf35,0xbf0ebec4,0xbf550000,0xbe483f6d,0x3f7bbf35,0xbf0ebec4,
0x3f0ebf80,0xbf7b3ec4,0x3e483f35,0x3f55bf6d,0x3f550000,0x3e48bf6d,0xbf7b3f35,0x3f0e3ec4,0xbf0e3f80,0x3f7bbec4,0xbe48bf35,0xbf553f6d,
0xbf353f80,0x3f350000,0x3f35bf80,0xbf350000,0xbf353f80,0x3f350000,0x3f35bf80,0xbf350000,0xbf353f80,0x3f350000,0x3f35bf80,0xbf350000,
0xbf353f80,0x3f350000,0x3f35bf80,0xbf350000,0xbf358000,0xbf353f80,0x3f358000,0x3f35bf80,0xbf358000,0xbf353f80,0x3f358000,0x3f35bf80,
0xbf358000,0xbf353f80,0x3f358000,0x3f35bf80,0xbf358000,0xbf353f80,0x3f358000,0x3f35bf80,0xbf0e0000,0xbf7b3f6d,0xbe483f35,0x3f55bec4,
0xbf553f80,0x3e483ec4,0x3f7bbf35,0x3f0ebf6d,0x3f0e0000,0x3f7bbf6d,0x3e48bf35,0xbf553ec4,0x3f55bf80,0xbe48bec4,0xbf7b3f35,0xbf0e3f6d,
0x3f55bf80,0xbe48bec4,0xbf7b3f35,0xbf0e3f6d,0xbf0e8000,0xbf7b3f6d,0xbe483f35,0x3f55bec4,0xbf553f80,0x3e483ec4,0x3f7bbf35,0x3f0ebf6d,
0x3f0e8000,0x3f7bbf6d,0x3e48bf35,0xbf553ec4,0xbf6d3f80,0xbec43f35,0x3ec40000,0x3f6dbf35,0x3f6dbf80,0x3ec4bf35,0xbec40000,0xbf6d3f35,
0xbf6d3f80,0xbec43f35,0x3ec40000,0x3f6dbf35,0x3f6dbf80,0x3ec4bf35,0xbec40000,0xbf6d3f35,0xbec48000,0xbf6d3f35,0xbf6d3f80,0xbec43f35,
0x3ec48000,0x3f6dbf35,0x3f6dbf80,0x3ec4bf35,0xbec48000,0xbf6d3f35,0xbf6d3f80,0xbec43f35,0x3ec48000,0x3f6dbf35,0x3f6dbf80,0x3ec4bf35,
0xbe480000,0xbf0e3ec4,0xbf553f35,0xbf7b3f6d,0x3f7bbf80,0x3f55bf6d,0x3f0ebf35,0x3e48bec4,0x3e480000,0x3f0ebec4,0x3f55bf35,0x3f7bbf6d,
0xbf7b3f80,0xbf553f6d,0xbf0e3f35,0xbe483ec4,0x3f7bbf80,0x3f55bf6d,0x3f0ebf35,0x3e48bec4,0x3e488000,0x3f0ebec4,0x3f55bf35,0x3f7bbf6d,
0xbf7b3f80,0xbf553f6d,0xbf0e3f35,0xbe483ec4,0xbe488000,0xbf0e3ec4,0xbf553f35,0xbf7b3f6d,0x80008000,0x80008000,0x80008000,0x80008000,
0x80008000,0x80008000,0x80008000,0x80008000,0x80008000,0x80008000,0x80008000,0x80008000,0x80008000,0x80008000,0x80008000,0x80008000,
0xbf803f80,0xbf803f80,0xbf803f80,0xbf803f80,0xbf803f80,0xbf803f80,0xbf803f80,0xbf803f80,0xbf803f80,0xbf803f80,0xbf803f80,0xbf803f80,
0xbf803f80,0xbf803f80,0xbf803f80,0xbf803f80,0x3f7bbf80,0x3f55bf6d,0x3f0ebf35,0x3e48bec4,0x3e488000,0x3f0ebec4,0x3f55bf35,0x3f7bbf6d,
0xbf7b3f80,0xbf553f6d,0xbf0e3f35,0xbe483ec4,0xbe488000,0xbf0e3ec4,0xbf553f35,0xbf7b3f6d,0x3e480000,0x3f0ebec4,0x3f55bf35,0x3f7bbf6d,
0xbf7b3f80,0xbf553f6d,0xbf0e3f35,0xbe483ec4,0xbe480000,0xbf0e3ec4,0xbf553f35,0xbf7b3f6d,0x3f7bbf80,0x3f55bf6d,0x3f0ebf35,0x3e48bec4,
0x3ec48000,0x3f6dbf35,0x3f6dbf80,0x3ec4bf35,0xbec48000,0xbf6d3f35,0xbf6d3f80,0xbec43f35,0x3ec48000,0x3f6dbf35,0x3f6dbf80,0x3ec4bf35,
0xbec48000,0xbf6d3f35,0xbf6d3f80,0xbec43f35,0xbf6d3f80,0xbec43f35,0x3ec40000,0x3f6dbf35,0x3f6dbf80,0x3ec4bf35,0xbec40000,0xbf6d3f35,
0xbf6d3f80,0xbec43f35,0x3ec40000,0x3f6dbf35,0x3f6dbf80,0x3ec4bf35,0xbec40000,0xbf6d3f35,0x3f55bf80,0xbe48bec4,0xbf7b3f35,0xbf0e3f6d,
0xbf0e8000,0xbf7b3f6d,0xbe483f35,0x3f55bec4,0xbf553f80,0x3e483ec4,0x3f7bbf35,0x3f0ebf6d,0x3f0e8000,0x3f7bbf6d,0x3e48bf35,0xbf553ec4,
0x3f0e0000,0x3f7bbf6d,0x3e48bf35,0xbf553ec4,0x3f55bf80,0xbe48bec4,0xbf7b3f35,0xbf0e3f6d,0xbf0e0000,0xbf7b3f6d,0xbe483f35,0x3f55bec4,
0xbf553f80,0x3e483ec4,0x3f7bbf35,0x3f0ebf6d,0xbf353f80,0x3f350000,0x3f35bf80,0xbf350000,0xbf353f80,0x3f350000,0x3f35bf80,0xbf350000,
0xbf353f80,0x3f350000,0x3f35bf80,0xbf350000,0xbf353f80,0x3f350000,0x3f35bf80,0xbf350000,0x3f358000,0x3f35bf80,0xbf358000,0xbf353f80,
0x3f358000,0x3f35bf80,0xbf358000,0xbf353f80,0x3f358000,0x3f35bf80,0xbf358000,0xbf353f80,0x3f358000,0x3f35bf80,0xbf358000,0xbf353f80,
0x3f550000,0x3e48bf6d,0xbf7b3f35,0x3f0e3ec4,0xbf0e3f80,0x3f7bbec4,0xbe48bf35,0xbf553f6d,0xbf550000,0xbe483f6d,0x3f7bbf35,0xbf0ebec4,
0x3f0ebf80,0xbf7b3ec4,0x3e483f35,0x3f55bf6d,0x3f0ebf80,0xbf7b3ec4,0x3e483f35,0x3f55bf6d,0x3f558000,0x3e48bf6d,0xbf7b3f35,0x3f0e3ec4,
0xbf0e3f80,0x3f7bbec4,0xbe48bf35,0xbf553f6d,0xbf558000,0xbe483f6d,0x3f7bbf35,0xbf0ebec4,0xbec43f80,0x3f6dbf35,0xbf6d0000,0x3ec43f35,
0x3ec4bf80,0xbf6d3f35,0x3f6d0000,0xbec4bf35,0xbec43f80,0x3f6dbf35,0xbf6d0000,0x3ec43f35,0x3ec4bf80,0xbf6d3f35,0x3f6d0000,0xbec4bf35,
0x3f6d8000,0xbec4bf35,0xbec43f80,0x3f6dbf35,0xbf6d8000,0x3ec43f35,0x3ec4bf80,0xbf6d3f35,0x3f6d8000,0xbec4bf35,0xbec43f80,0x3f6dbf35,
0xbf6d8000,0x3ec43f35,0x3ec4bf80,0xbf6d3f35,0x3f7b0000,0xbf55bec4,0x3f0e3f35,0xbe48bf6d,0x3e48bf80,0xbf0e3f6d,0x3f55bf35,0xbf7b3ec4,
0xbf7b0000,0x3f553ec4,0xbf0ebf35,0x3e483f6d,0xbe483f80,0x3f0ebf6d,0xbf553f35,0x3f7bbec4,0x3e48bf80,0xbf0e3f6d,0x3f55bf35,0xbf7b3ec4,
0xbf7b8000,0x3f553ec4,0xbf0ebf35,0x3e483f6d,0xbe483f80,0x3f0ebf6d,0xbf553f35,0x3f7bbec4,0x3f7b8000,0xbf55bec4,0x3f0e3f35,0xbe48bf6d,
0x3f808000,0xbf808000,0x3f808000,0xbf808000,0x3f808000,0xbf808000,0x3f808000,0xbf808000,0x3f808000,0xbf808000,0x3f808000,0xbf808000,
0x3f808000,0xbf808000,0x3f808000,0xbf808000,0x3f80,0xbf80,0x3f80,0xbf80,0x3f80,0xbf80,0x3f80,0xbf80,
0x3f80,0xbf80,0x3f80,0xbf80,0x3f80,0xbf80,0x3f80,0xbf80,0xbe48bf80,0x3f0e3f6d,0xbf55bf35,0x3f7b3ec4,
0x3f7b8000,0xbf553ec4,0x3f0ebf35,0xbe483f6d,0x3e483f80,0xbf0ebf6d,0x3f553f35,0xbf7bbec4,0xbf7b8000,0x3f55bec4,0xbf0e3f35,0x3e48bf6d,
0x3f7b0000,0xbf553ec4,0x3f0ebf35,0xbe483f6d,0x3e483f80,0xbf0ebf6d,0x3f553f35,0xbf7bbec4,0xbf7b0000,0x3f55bec4,0xbf0e3f35,0x3e48bf6d,
0xbe48bf80,0x3f0e3f6d,0xbf55bf35,0x3f7b3ec4,0x3f6d8000,0xbec43f35,0xbec4bf80,0x3f6d3f35,0xbf6d8000,0x3ec4bf35,0x3ec43f80,0xbf6dbf35,
0x3f6d8000,0xbec43f35,0xbec4bf80,0x3f6d3f35,0xbf6d8000,0x3ec4bf35,0x3ec43f80,0xbf6dbf35,0x3ec43f80,0xbf6dbf35,0x3f6d0000,0xbec43f35,
0xbec4bf80,0x3f6d3f35,0xbf6d0000,0x3ec4bf35,0x3ec43f80,0xbf6dbf35,0x3f6d0000,0xbec43f35,0xbec4bf80,0x3f6d3f35,0xbf6d0000,0x3ec4bf35,
0xbf0ebf80,0x3f7b3ec4,0xbe483f35,0xbf55bf6d,0xbf558000,0xbe48bf6d,0x3f7b3f35,0xbf0e3ec4,0x3f0e3f80,0xbf7bbec4,0x3e48bf35,0x3f553f6d,
0x3f558000,0x3e483f6d,0xbf7bbf35,0x3f0ebec4,0x3f550000,0x3e483f6d,0xbf7bbf35,0x3f0ebec4,0xbf0ebf80,0x3f7b3ec4,0xbe483f35,0xbf55bf6d,
0xbf550000,0xbe48bf6d,0x3f7b3f35,0xbf0e3ec4,0x3f0e3f80,0xbf7bbec4,0x3e48bf35,0x3f553f6d,0x3f353f80,0xbf350000,0xbf35bf80,0x3f350000,
0x3f353f80,0xbf350000,0xbf35bf80,0x3f350000,0x3f353f80,0xbf350000,0xbf35bf80,0x3f350000,0x3f353f80,0xbf350000,0xbf35bf80,0x3f350000,
0x3f358000,0x3f353f80,0xbf358000,0xbf35bf80,0x3f358000,0x3f353f80,0xbf358000,0xbf35bf80,0x3f358000,0x3f353f80,0xbf358000,0xbf35bf80,
0x3f358000,0x3f353f80,0xbf358000,0xbf35bf80,0x3f0e0000,0x3f7b3f6d,0x3e483f35,0xbf55bec4,0x3f553f80,0xbe483ec4,0xbf7bbf35,0xbf0ebf6d,
0xbf0e0000,0xbf7bbf6d,0xbe48bf35,0x3f553ec4,0xbf55bf80,0x3e48bec4,0x3f7b3f35,0x3f0e3f6d,0xbf55bf80,0x3e48bec4,0x3f7b3f35,0x3f0e3f6d,
0x3f0e8000,0x3f7b3f6d,0x3e483f35,0xbf55bec4,0x3f553f80,0xbe483ec4,0xbf7bbf35,0xbf0ebf6d,0xbf0e8000,0xbf7bbf6d,0xbe48bf35,0x3f553ec4,
0x3f6d3f80,0x3ec43f35,0xbec40000,0xbf6dbf35,0xbf6dbf80,0xbec4bf35,0x3ec40000,0x3f6d3f35,0x3f6d3f80,0x3ec43f35,0xbec40000,0xbf6dbf35,
0xbf6dbf80,0xbec4bf35,0x3ec40000,0x3f6d3f35,0x3ec48000,0x3f6d3f35,0x3f6d3f80,0x3ec43f35,0xbec48000,0xbf6dbf35,0xbf6dbf80,0xbec4bf35,
0x3ec48000,0x3f6d3f35,0x3f6d3f80,0x3ec43f35,0xbec48000,0xbf6dbf35,0xbf6dbf80,0xbec4bf35,0x3e480000,0x3f0e3ec4,0x3f553f35,0x3f7b3f6d,
0xbf7bbf80,0xbf55bf6d,0xbf0ebf35,0xbe48bec4,0xbe480000,0xbf0ebec4,0xbf55bf35,0xbf7bbf6d,0x3f7b3f80,0x3f553f6d,0x3f0e3f35,0x3e483ec4,
0xbf7bbf80,0xbf55bf6d,0xbf0ebf35,0xbe48bec4,0xbe488000,0xbf0ebec4,0xbf55bf35,0xbf7bbf6d,0x3f7b3f80,0x3f553f6d,0x3f0e3f35,0x3e483ec4,
0x3e488000,0x3f0e3ec4,0x3f553f35,0x3f7b3f6d,0x3f803f80,0x80008000,0x3f803f80,0x80008000,0x3f803f80,0x80008000,0x3f803f80,0x80008000,
0x3f803f80,0x80008000,0x3f803f80,0x80008000,0x3f803f80,0x80008000,0x3f803f80,0x80008000,0x3f803f80,0xbbc98000,0x3f803f80,0xbd62bd49,
0x3f803f80,0xbc97bc49,0x3f7f3f80,0xbd8abd7b,0x3f803f80,0xbcfbbcc9,0x3f7f3f7f,0xbda3bd97,0x3f803f80,0xbd30bd17,0x3f7f3f7f,0xbdbcbdb0,
0x3f803f80,0xbc498000,0x3f7e3f7f,0xbde2bdc9,0x3f803f80,0xbd17bcc9,0x3f7e3f7e,0xbe0abdfb,0x3f803f80,0xbd7bbd49,0x3f7d3f7d,0xbe23be16,
0x3f7f3f7f,0xbdb0bd97,0x3f7c3f7c,0xbe3bbe2f,0x3f803f80,0xbc978000,0x3f7c3f7d,0xbe29be16,0x3f803f80,0xbd62bd17,0x3f7b3f7c,0xbe4ebe3b,
0x3f7f3f7f,0xbdbcbd97,0x3f793f7a,0xbe73be60,0x3f7e3f7e,0xbe04bde2,0x3f763f78,0xbe8cbe82,0x3f803f80,0xbcc98000,0x3f7a3f7b,0xbe60be48,
0x3f7f3f80,0xbd97bd49,0x3f773f78,0xbe89be79,0x3f7e3f7f,0xbdfbbdc9,0x3f733f75,0xbea1be95,0x3f7c3f7d,0xbe2fbe16,0x3f6f3f71,0xbeb8beac,
0x3f803f80,0xbcfb8000,0x3f763f78,0xbe8cbe79,0x3f7f3f80,0xbdbcbd7b,0x3f723f74,0xbeaabe9b,0x3f7d3f7e,0xbe1cbdfb,0x3f6c3f6f,0xbec7beb8,
0x3f7a3f7c,0xbe5abe3b,0x3f653f69,0xbee3bed5,0x3f803f80,0xbd178000,0x3f723f75,0xbea7be95,0x3f7e3f7f,0xbde2bd97,0x3f6b3f6f,0xbecabeb8,
0x3f7c3f7d,0xbe3bbe16,0x3f633f67,0xbeecbedb,0x3f783f7a,0xbe82be60,0x3f5a3f5f,0xbf06befc,0x3f803f80,0xbd308000,0x3f6d3f71,0xbec1beac,
0x3f7e3f7f,0xbe04bdb0,0x3f643f69,0xbee9bed5,0x3f7a3f7c,0xbe5abe2f,0x3f593f5f,0xbf08befc,0x3f753f78,0xbe98be82,0x3f4d3f53,0xbf1abf11,
0x3f803f80,0x80008000,0x3f803f80,0x80008000,0x3f803f80,0x80008000,0x3f803f80,0x80008000,0x3f803f80,0x80008000,0x3f803f80,0x80008000,
0x3f803f80,0x80008000,0x3f803f80,0x80008000,0x3f7f3f7f,0xbdd5bdc9,0x3f7d3f7d,0xbe1cbe16,0x3f7e3f7e,0xbdeebde2,0x3f7c3f7d,0xbe29be23,
0x3f7e3f7e,0xbe04bdfb,0x3f7c3f7c,0xbe35be2f,0x3f7d3f7e,0xbe10be0a,0x3f7b3f7c,0xbe42be3b,0x3f7a3f7b,0xbe54be48,0x3f743f75,0xbe9bbe95,
0x3f793f7a,0xbe6dbe60,0x3f723f73,0xbea7bea1,0x3f783f78,0xbe82be79,0x3f703f71,0xbeb2beac,0x3f763f77,0xbe8fbe89,0x3f6e3f6f,0xbebebeb8,
0x3f743f75,0xbe9ebe95,0x3f653f67,0xbee3bedb,0x3f713f72,0xbeafbea7,0x3f613f63,0xbef4beec,0x3f6d3f6f,0xbec1beb8,0x3f5c3f5f,0xbf02befc,
0x3f693f6b,0xbed2beca,0x3f573f5a,0xbf0abf06,0x3f6a3f6d,0xbecfbec4,0x3f513f55,0xbf13bf0e,0x3f653f67,0xbee6bedb,0x3f4a3f4e,0xbf1dbf18,
0x3f5f3f62,0xbefcbef1,0x3f423f46,0xbf27bf22,0x3f583f5c,0xbf09bf04,0x3f393f3e,0xbf31bf2c,0x3f5e3f62,0xbeffbef1,0x3f383f3e,0xbf32bf2c,
0x3f563f5a,0xbf0dbf06,0x3f2d3f33,0xbf3dbf37,0x3f4d3f51,0xbf1abf13,0x3f213f27,0xbf47bf42,0x3f433f48,0xbf26bf20,0x3f153f1b,0xbf50bf4c,
0x3f4f3f55,0xbf16bf0e,0x3f1b3f22,0xbf4cbf46,0x3f443f4a,0xbf25bf1d,0x3f0c3f13,0xbf57bf51,0x3f373f3e,0xbf33bf2c,0x3ef73f04,0xbf60bf5c,
0x3f2a3f31,0xbf40bf39,0x3ed53ee6,0xbf69bf65,0x3f3f3f46,0xbf2bbf22,0x3ef43f04,0xbf61bf5c,0x3f2f3f37,0xbf3abf33,0x3ecd3ee1,0xbf6bbf66,
0x3f1f3f27,0xbf49bf42,0x3ea43eb8,0xbf73bf6f,0x3f0d3f16,0xbf56bf4f,0x3e733e8f,0xbf79bf76,0x3f803f80,0xbd498000,0x3f673f6d,0xbedbbec4,
0x3f7d3f7f,0xbe16bdc9,0x3f5c3f62,0xbf04bef1,0x3f783f7b,0xbe79be48,0x3f4e3f55,0xbf18bf0e,0x3f713f75,0xbeacbe95,0x3f3e3f46,0xbf2cbf22,
0x3f803f80,0xbd628000,0x3f613f67,0xbef4bedb,0x3f7c3f7e,0xbe29bde2,0x3f523f5a,0xbf12bf06,0x3f763f7a,0xbe8cbe60,0x3f413f4a,0xbf28bf1d,
0x3f6d3f72,0xbec1bea7,0x3f2d3f37,0xbf3dbf33,0x3f803f80,0xbd7b8000,0x3f5a3f62,0xbf06bef1,0x3f7c3f7e,0xbe3bbdfb,0x3f483f51,0xbf20bf13,
0x3f743f78,0xbe9bbe79,0x3f333f3e,0xbf37bf2c,0x3f693f6f,0xbed5beb8,0x3f1b3f27,0xbf4cbf42,0x3f7f3f80,0xbd8a8000,0x3f523f5c,0xbf12bf04,
0x3f7b3f7e,0xbe4ebe0a,0x3f3d3f48,0xbf2dbf20,0x3f723f77,0xbeaabe89,0x3f243f31,0xbf45bf39,0x3f643f6b,0xbee9beca,0x3f083f16,0xbf59bf4f,
0x3f7f3f80,0xbd978000,0x3f4a3f55,0xbf1dbf0e,0x3f7a3f7d,0xbe60be16,0x3f313f3e,0xbf39bf2c,0x3f6f3f75,0xbeb8be95,0x3f133f22,0xbf51bf46,
0x3f5f3f67,0xbefcbedb,0x3ee63f04,0xbf65bf5c,0x3f7f3f80,0xbda38000,0x3f413f4e,0xbf28bf18,0x3f793f7d,0xbe73be23,0x3f243f33,0xbf45bf37,
0x3f6c3f73,0xbec7bea1,0x3f023f13,0xbf5cbf51,0x3f593f63,0xbf08beec,0x3ebb3ee1,0xbf6ebf66,0x3f7f3f80,0xbdb08000,0x3f373f46,0xbf33bf22,
0x3f783f7c,0xbe82be2f,0x3f163f27,0xbf4fbf42,0x3f693f71,0xbed5beac,0x3ee13f04,0xbf66bf5c,0x3f533f5f,0xbf11befc,0x3e8f3eb8,0xbf76bf6f,
0x3f7f3f80,0xbdbc8000,0x3f2d3f3e,0xbf3dbf2c,0x3f763f7c,0xbe8cbe3b,0x3f083f1b,0xbf59bf4c,0x3f653f6f,0xbee3beb8,0x3ebb3ee6,0xbf6ebf65,
0x3f4d3f5a,0xbf1abf06,0x3e423e8f,0xbf7bbf76,0x3f2c3f35,0xbf3ebf35,0x3eac3ec4,0xbf71bf6d,0x3f183f22,0xbf4ebf46,0x3e793e95,0xbf78bf75,
0x3f043f0e,0xbf5cbf55,0x3e163e48,0xbf7dbf7b,0x3edb3ef1,0xbf67bf62,0x3d493dc9,0xbf80bf7f,0x3f173f22,0xbf4fbf46,0x3e423e79,0xbf7bbf78,
0x3eff3f0c,0xbf5ebf57,0x3da33e0a,0xbf7fbf7e,0x3ecd3ee6,0xbf6bbf65,0xbcfb3cc9,0xbf80bf80,0x3e983eb2,0xbf75bf70,0xbe10bdb0,0xbf7dbf7f,
0x3f013f0e,0xbf5dbf55,0x3d173dc9,0xbf80bf7f,0x3eca3ee6,0xbf6bbf65,0xbdb0bcc9,0xbf7fbf80,0x3e8f3eac,0xbf76bf71,0xbe54be16,0xbf7abf7d,
0x3e233e60,0xbf7dbf7a,0xbea7be89,0xbf72bf77,0x3ed23ef1,0xbf69bf62,0xbdeebd49,0xbf7ebf80,0x3e923eb2,0xbf75bf70,0xbe7fbe3b,0xbf78bf7c,
0x3e1c3e60,0xbf7dbf7a,0xbec1bea1,0xbf6dbf73,0x3c973db0,0xbf80bf7f,0xbeffbee1,0xbf5ebf66,0x3ea13ec4,0xbf73bf6d,0xbe89be48,0xbf77bf7b,
0x3e2f3e79,0xbf7cbf78,0xbecfbeac,0xbf6abf71,0x3cc93dc9,0xbf80bf7f,0xbf09bef1,0xbf58bf62,0xbdfbbd49,0xbf7ebf80,0xbf27bf18,0xbf42bf4e,
0x3e5a3e95,0xbf7abf75,0xbed2beac,0xbf69bf71,0x3d623e0a,0xbf80bf7e,0xbf0dbef7,0xbf56bf60,0xbdd5bcc9,0xbf7fbf80,0xbf2dbf1d,0xbf3dbf4a,
0xbe86be3b,0xbf77bf7c,0xbf49bf3c,0xbf1fbf2e,0x3de23e48,0xbf7ebf7b,0xbf0cbef1,0xbf57bf62,0xbd7b3cc9,0xbf80bf80,0xbf2ebf1d,0xbf3cbf4a,
0xbe6dbe16,0xbf79bf7d,0xbf4cbf3e,0xbf1bbf2c,0xbecabea1,0xbf6bbf73,0xbf63bf58,0xbeecbf09,0x3bc93dc9,0xbf80bf7f,0xbf2bbf18,0xbf3fbf4e,
0xbe35bdb0,0xbf7cbf7f,0xbf4bbf3c,0xbf1cbf2e,0xbeb5be89,0xbf6fbf77,0xbf64bf58,0xbee9bf09,0xbf05bee1,0xbf5bbf66,0xbf75bf6e,0xbe92bebe,
0x3f7f3f80,0xbdc98000,0x3f223f35,0xbf46bf35,0x3f753f7b,0xbe95be48,0x3ef13f0e,0xbf62bf55,0x3f623f6d,0xbef1bec4,0x3e953ec4,0xbf75bf6d,
0x3f463f55,0xbf22bf0e,0x3dc93e48,0xbf7fbf7b,0x3f7f3f80,0xbdd58000,0x3f173f2c,0xbf4fbf3e,0x3f743f7a,0xbe9ebe54,0x3ed23f01,0xbf69bf5d,
0x3f5e3f6a,0xbeffbecf,0x3e5a3ea1,0xbf7abf73,0x3f3f3f4f,0xbf2bbf16,0x3bc93de2,0xbf80bf7e,0x3f7e3f80,0xbde28000,0x3f0c3f22,0xbf57bf46,
0x3f723f7a,0xbea7be60,0x3eb23ee6,0xbf70bf65,0x3f5a3f67,0xbf06bedb,0x3e0a3e79,0xbf7ebf78,0x3f373f4a,0xbf33bf1d,0xbdb03cc9,0xbf7fbf80,
0x3f7e3f80,0xbdee8000,0x3eff3f18,0xbf5ebf4e,0x3f713f79,0xbeafbe6d,0x3e923eca,0xbf75bf6b,0x3f563f65,0xbf0dbee6,0x3d623e2f,0xbf80bf7c,
0x3f2f3f44,0xbf3abf25,0xbe35bd7b,0xbf7cbf80,0x3f7e3f80,0xbdfb8000,0x3ee63f0e,0xbf65bf55,0x3f6f3f78,0xbeb8be79,0x3e603eac,0xbf7abf71,
0x3f513f62,0xbf13bef1,0xbcc93dc9,0xbf80bf7f,0x3f273f3e,0xbf42bf2c,0xbe89be16,0xbf77bf7d,0x3f7e3f80,0xbe048000,0x3ecd3f04,0xbf6bbf5c,
0x3f6d3f78,0xbec1be82,0x3e1c3e8f,0xbf7dbf76,0x3f4d3f5f,0xbf1abefc,0xbdd53cc9,0xbf7fbf80,0x3f1f3f37,0xbf49bf33,0xbeb5be6d,0xbf6fbf79,
0x3f7e3f80,0xbe0a8000,0x3eb23ef1,0xbf70bf62,0x3f6b3f77,0xbecabe89,0x3db03e60,0xbf7fbf7a,0x3f483f5c,0xbf20bf04,0xbe3bbd49,0xbf7cbf80,
0x3f163f31,0xbf4fbf39,0xbee1bea1,0xbf66bf73,0x3f7d3f80,0xbe108000,0x3e983edb,0xbf75bf67,0x3f693f76,0xbed2be8f,0x3c973e23,0xbf80bf7d,
0x3f433f58,0xbf26bf09,0xbe86bdfb,0xbf77bf7e,0x3f0d3f2a,0xbf56bf40,0xbf05beca,0xbf5bbf6b,0xbdc90000,0xbf7fbf80,0xbf46bf35,0xbf22bf35,
0xbe95be48,0xbf75bf7b,0xbf62bf55,0xbef1bf0e,0xbef1bec4,0xbf62bf6d,0xbf75bf6d,0xbe95bec4,0xbf22bf0e,0xbf46bf55,0xbf7fbf7b,0xbdc9be48,
0xbe4ebdc9,0xbf7bbf7f,0xbf5cbf4e,0xbf02bf18,0xbecdbe9b,0xbf6bbf74,0xbf73bf69,0xbea4bed5,0xbf15befc,0xbf50bf5f,0xbf7ebf7a,0xbdeebe60,
0xbf3dbf2a,0xbf2dbf40,0xbf7fbf80,0x3dbcbc49,0xbe9bbe48,0xbf74bf7b,0xbf6ebf62,0xbebebef1,0xbf01becf,0xbf5dbf6a,0xbf7dbf77,0xbe23be89,
0xbf2ebf18,0xbf3cbf4e,0xbf80bf80,0x3d7bbd49,0xbf53bf42,0xbf11bf27,0xbf76bf7c,0x3e8f3e2f,0xbecdbe95,0xbf6bbf75,0xbf79bf71,0xbe66beac,
0xbf1abf01,0xbf4dbf5d,0xbf80bf7e,0x3bc9bde2,0xbf45bf31,0xbf24bf39,0xbf79bf7e,0x3e733dfb,0xbf65bf57,0xbee3bf0c,0xbf64bf70,0x3ee93eb2,
0xbefcbec4,0xbf5fbf6d,0xbf7fbf7b,0xbd97be48,0xbf31bf18,0xbf39bf4e,0xbf7cbf80,0x3e2f3d49,0xbf58bf46,0xbf09bf22,0xbf6abf75,0x3ecf3e95,
0xbf73bf67,0xbea1bedb,0xbf4abf5c,0x3f1d3f04,0xbf15bef1,0xbf50bf62,0xbf7fbf80,0x3da3bd49,0xbf45bf2e,0xbf24bf3c,0xbf72bf7a,0x3eaa3e54,
0xbf68bf58,0xbed8bf09,0xbf54bf65,0x3f103ee6,0xbf7cbf74,0xbe35be9b,0xbf28bf40,0x3f413f2a,0xbf2abf0e,0xbf40bf55,0xbf79bf7f,0x3e6d3dc9,
0xbf57bf42,0xbf0cbf27,0xbf60bf6f,0x3ef73eb8,0xbf74bf67,0xbe9bbedb,0xbf37bf4e,0x3f333f18,0xbf80bf7c,0xbd17be2f,0xbf01bf1d,0x3f5d3f4a,
0xbf3dbf22,0xbf2dbf46,0xbf6dbf78,0x3ec13e79,0xbf65bf53,0xbee3bf11,0xbf49bf5d,0x3f1f3f01,0xbf7cbf73,0xbe35bea1,0xbf15bf31,0x3f503f39,
0xbf7fbf80,0x3dd5bd17,0xbeaabeec,0x3f723f63,0x3f7d3f80,0xbe168000,0x3e793ec4,0xbf78bf6d,0x3f673f75,0xbedbbe95,0xbd493dc9,0xbf80bf7f,
0x3f3e3f55,0xbf2cbf0e,0xbeacbe48,0xbf71bf7b,0x3f043f22,0xbf5cbf46,0xbf18bef1,0xbf4ebf62,0x3f7d3f80,0xbe1c8000,0x3e423eac,0xbf7bbf71,
0x3f653f74,0xbee3be9b,0xbdee3d17,0xbf7ebf80,0x3f383f51,0xbf32bf13,0xbed2be89,0xbf69bf77,0x3ef43f1b,0xbf61bf4c,0xbf2bbf0c,0xbf3fbf57,
0x3f7d3f80,0xbe238000,0x3e0a3e95,0xbf7ebf75,0x3f633f73,0xbeecbea1,0xbe3bbcc9,0xbf7cbf80,0x3f333f4e,0xbf37bf18,0xbef7beac,0xbf60bf71,
0x3ee13f13,0xbf66bf51,0xbf3cbf1d,0xbf2ebf4a,0x3f7c3f80,0xbe298000,0x3da33e79,0xbf7fbf78,0x3f613f72,0xbef4bea7,0xbe7fbdb0,0xbf78bf7f,
0x3f2d3f4a,0xbf3dbf1d,0xbf0dbecf,0xbf56bf6a,0x3ecd3f0c,0xbf6bbf57,0xbf4bbf2e,0xbf1cbf3c,0x3f7c3f80,0xbe2f8000,0x3cc93e48,0xbf80bf7b,
0x3f5f3f71,0xbefcbeac,0xbea1be16,0xbf73bf7d,0x3f273f46,0xbf42bf22,0xbf1dbef1,0xbf4abf62,0x3eb83f04,0xbf6fbf5c,0xbf58bf3e,0xbf09bf2c,
0x3f7c3f80,0xbe358000,0xbcfb3e16,0xbf80bf7d,0x3f5c3f70,0xbf02beb2,0xbec1be54,0xbf6dbf7a,0x3f213f42,0xbf47bf27,0xbf2dbf09,0xbf3dbf58,
0x3ea43ef7,0xbf73bf60,0xbf64bf4c,0xbee9bf1b,0x3f7c3f80,0xbe3b8000,0xbdb03dc9,0xbf7fbf7f,0x3f5a3f6f,0xbf06beb8,0xbee1be89,0xbf66bf77,
0x3f1b3f3e,0xbf4cbf2c,0xbf3cbf18,0xbf2ebf4e,0x3e8f3ee6,0xbf76bf65,0xbf6ebf58,0xbebebf09,0x3f7b3f80,0xbe428000,0xbe103d49,0xbf7dbf80,
0x3f573f6e,0xbf0abebe,0xbeffbea7,0xbf5ebf72,0x3f153f39,0xbf50bf31,0xbf49bf27,0xbf1fbf42,0x3e733ed5,0xbf79bf69,0xbf75bf63,0xbe92beec,
0xbf4ebf35,0xbf18bf35,0xbf5cbf6d,0x3f043ec4,0xbf71bf62,0xbeacbef1,0xbf2cbf46,0x3f3e3f22,0xbf80bf7b,0xbd49be48,0xbedbbf0e,0x3f673f55,
0xbf78bf7f,0x3e793dc9,0xbe16be95,0x3f7d3f75,0xbf5cbf46,0xbf02bf22,0xbf45bf5c,0x3f243f04,0xbf79bf6e,0xbe66bebe,0xbf0abf2a,0x3f573f40,
0xbf7fbf7f,0x3da3bd97,0xbe86becf,0x3f773f6a,0xbf6dbf79,0x3ec13e6d,0x3d30bde2,0x3f803f7e,0xbf69bf55,0xbed5bf0e,0xbf2abf46,0x3f403f22,
0xbf7ebf77,0xbde2be89,0xbecabf09,0x3f6b3f58,0xbf7abf80,0x3e543d49,0xbdb0be79,0x3f7f3f78,0xbf5dbf6f,0x3f013eb8,0x3e6d3d97,0x3f793f7f,
0xbf73bf62,0xbea4bef1,0xbf0abf2c,0x3f573f3e,0xbf80bf7d,0x3bc9be23,0xbe73beca,0x3f793f6b,0xbf72bf7c,0x3eaa3e2f,0x3dbcbd97,0x3f7f3f7f,
0xbf49bf60,0x3f1f3ef7,0x3ed23e82,0x3f693f78,0xbf7abf6d,0xbe60bec4,0xbecfbf0e,0x3f6a3f55,0xbf7ebf80,0x3dfbbd49,0xbd97be79,0x3f7f3f78,
0xbf65bf75,0x3ee63e95,0x3e893dc9,0x3f773f7f,0xbf31bf4e,0x3f393f18,0x3f133edb,0x3f513f67,0xbf7ebf75,0xbdeebe95,0xbe86bedb,0x3f773f67,
0xbf79bf80,0x3e733d7b,0x3dbcbdb0,0x3f7f3f7f,0xbf54bf6a,0x3f103ecf,0x3ede3e89,0x3f673f77,0xbf15bf37,0x3f503f33,0x3f383f16,0x3f323f4f,
0xbf80bf7b,0xbc49be48,0xbde2be95,0x3f7e3f75,0xbf70bf7c,0x3eb23e2f,0x3e823d97,0x3f783f7f,0xbf40bf5c,0x3f2a3f04,0x3f163edb,0x3f4f3f67,
0xbeecbf1d,0x3f633f4a,0x3f573f39,0x3f0c3f31,0xbf7fbf7f,0x3dbcbdc9,0x3d30be16,0x3f803f7d,0xbf64bf76,0x3ee93e8f,0x3ed23e6d,0x3f693f79,
0xbf28bf4a,0x3f413f1d,0x3f383f13,0x3f323f51,0xbeaabf01,0x3f723f5d,0x3f6d3f57,0x3ec13f0c,
};
__device__ const __align__(128) uint64_t c_inv[16384] = {
0x3f003f003f003f00,0x3f003f003f003f00,0x3f003f003f003f00,0x3f003f003f003f00,0x3f003f003f003f00,0x3f003f003f003f00,0x3f003f003f003f00,0x3f003f003f003f00,
0xbf00bf003f003f00,0xbf00bf003f003f00,0xbf00bf003f003f00,0xbf00bf003f003f00,0xbf00bf003f003f00,0xbf00bf003f003f00,0xbf00bf003f003f00,0xbf00bf003f003f00,
0x3f733f7a3f753f7b,0x3f6f3f773f713f78,0x3f7e3f803f7f3f80,0x3f7c3f7f3f7d3f80,0x3f423f513f463f55,0x3f393f4a3f3e3f4e,0x3f5f3f6a3f623f6d,0x3f583f653f5c3f67,
0xbea1be60be95be48,0xbeb8be89beacbe79,0xbdfbbcc9bdc98000,0xbe2fbd97be16bd49,0xbf27bf13bf22bf0e,0xbf31bf1dbf2cbf18,0xbefcbecfbef1bec4,0xbf09bee6bf04bedb,
0x3f043f2c3f0e3f35,0x3edb3f183ef13f22,0x3e163eac3e483ec4,0x3d493e793dc93e95,0x3f783f803f7b3f80,0x3f713f7d3f753f7f,0x3f4e3f673f553f6d,0x3f3e3f5c3f463f62,
0xbf5cbf3ebf55bf35,0xbf67bf4ebf62bf46,0xbf7dbf71bf7bbf6d,0xbf80bf78bf7fbf75,0xbe79bd49be488000,0xbeacbe16be95bdc9,0xbf18bedbbf0ebec4,0xbf2cbf04bf22bef1,
0xbf09be89bef1be48,0xbf27becfbf18beac,0x3cc93ea13dc93ec4,0xbdfb3e2fbd493e79,0x3f133f4a3f223f55,0x3ee63f313f043f3e,0x3f6f3f7f3f753f80,0x3f5f3f7a3f673f7d,
0xbf58bf77bf62bf7b,0xbf42bf6abf4ebf71,0xbf80bf73bf7fbf6d,0xbf7ebf7cbf80bf78,0xbf51bf1dbf46bf0e,0xbf65bf39bf5cbf2c,0xbeb8bd97be958000,0xbefcbe60bedbbe16,
0x3f623f7f3f6d3f80,0x3f463f753f553f7b,0x3e953f223ec43f35,0x3dc93ef13e483f0e,0xbef1bdc9bec40000,0xbf22be95bf0ebe48,0xbf75bf46bf6dbf35,0xbf7fbf62bf7bbf55,
0xbef1bdc9bec48000,0xbf22be95bf0ebe48,0xbf75bf46bf6dbf35,0xbf7fbf62bf7bbf55,0xbf62bf7fbf6dbf80,0xbf46bf75bf55bf7b,0xbe95bf22bec4bf35,0xbdc9bef1be48bf0e,
0xbcc93ee63dc93f0e,0xbe893e60be163eac,0x3f513f7e3f623f80,0x3f273f6f3f3e3f78,0xbf6abf7fbf75bf7b,0xbf4abf7cbf5cbf80,0xbf58befcbf46bec4,0xbf73bf31bf67bf18,
0xbf80bf65bf7fbf55,0xbf77bf7abf7dbf71,0xbf13bdfbbef18000,0xbf42beb8bf2cbe79,0x3ecfbd973e95be48,0x3f1d3e2f3f043d49,0xbf09bf5fbf22bf6d,0xbea1bf39bedbbf4e,
0xbf80bf4ebf7bbf35,0xbf78bf71bf7fbf62,0xbedbbf5cbf0ebf6d,0xbe16bf2cbe95bf46,0x3f3e3f7d3f553f80,0x3f043f673f223f75,0xbeac3e79be483ec4,0xbf18bd49bef13dc9,
0xbd49bf18be48bf35,0x3e79beac3dc9bef1,0x3f673f043f553ec4,0x3f7d3f3e3f753f22,0xbf2cbe16bf0e8000,0xbf5cbedbbf46be95,0xbf71bf78bf7bbf6d,0xbf4ebf80bf62bf7f,
0x3e89becf3dc9bf0e,0x3f13bd973edbbe79,0xbf65bf7abf75bf6d,0xbf31bf7ebf4ebf80,0xbf1d3cc9bef13e48,0xbf58bea1bf3ebe16,0x3f273f7c3f463f80,0x3eb83f5f3f043f71,
0x3f773f6a3f7f3f55,0x3f513f7f3f673f78,0x3ee6be603e95bec4,0x3f393dfb3f18bd49,0xbf4abf80bf62bf7b,0xbf09bf73bf2cbf7d,0xbf42be2fbf228000,0xbf6fbefcbf5cbeac,
0x3f0e3f7b3f353f80,0x3e483f553ec43f6d,0xbf55be48bf350000,0xbf7bbf0ebf6dbec4,0xbf0ebf7bbf35bf80,0xbe48bf55bec4bf6d,0x3f553e483f350000,0x3f7b3f0e3f6d3ec4,
0xbf55be48bf358000,0xbf7bbf0ebf6dbec4,0xbf0ebf7bbf35bf80,0xbe48bf55bec4bf6d,0x3f553e483f358000,0x3f7b3f0e3f6d3ec4,0x3f0e3f7b3f353f80,0x3e483f553ec43f6d,
0xbf77becfbf62be48,0xbf7cbf42bf80bf18,0x3ee63f7a3f223f80,0x3cc93f4a3e793f67,0x3f7e3f393f7f3f0e,0x3f583f733f713f5c,0xbd97bf51be95bf6d,0x3eb8befc3e16bf2c,
0xbe89bf6abef1bf7b,0x3e2fbf27bd49bf4e,0xbf65be60bf468000,0xbf80bf1dbf78bedb,0xbdfb3f313dc93f55,0xbf093ea1beac3f04,0x3f7f3f133f753ec4,0x3f6f3f5f3f7d3f3e,
0x3edbbf043e48bf35,0x3f4ebd493f22be95,0x3f2c3f7d3f553f6d,0x3e793f713ef13f7f,0x3eac3f783f0e3f80,0xbe163f3e3dc93f62,0xbf80bf18bf7bbec4,0xbf5cbf67bf75bf46,
0x3f673f5c3f7b3f35,0x3f183f803f463f75,0xbf3e3e16bf0e3ec4,0xbf78beacbf62bdc9,0xbf71be79bf558000,0xbf7dbf2cbf7fbef1,0x3d49bf4ebe48bf6d,0x3f04bedb3e95bf22,
0x3cc93f653e953f7b,0xbefc3f09be793f3e,0x3f51bdfb3f22bec4,0x3f7f3ecf3f713e16,0xbf6fbf42bf7fbf0e,0xbf1dbf7cbf4ebf67,0x3e603f773ef13f80,0xbea13f31bd493f5c,
0xbf80bee6bf75be48,0xbf5fbf58bf78bf2c,0x3f133f7e3f463f6d,0x3d973f6a3eac3f7d,0x3eb8bf273dc9bf55,0x3f4abe2f3f18bedb,0xbf7abe89bf628000,0xbf73bf39bf80bf04,
0x3dc93f753ec43f80,0xbef13f22be483f55,0xbf46bf62bf6dbf35,0xbe95bf7fbf0ebf7b,0x3f7f3e953f6d0000,0x3f623f463f7b3f0e,0xbf223ef1bec43f35,0xbf75bdc9bf553e48,
0xbf7fbe95bf6d8000,0xbf62bf46bf7bbf0e,0x3f22bef13ec4bf35,0x3f753dc93f55be48,0x3dc93f753ec43f80,0xbef13f22be483f55,0xbf46bf62bf6dbf35,0xbe95bf7fbf0ebf7b,
0xbf09bf77bf46bf55,0x3d97bf6fbe79bf80,0xbcc93f733e953f80,0xbf1d3f13beac3f4e,0xbf7cbdfbbf623e48,0xbf65bf31bf7dbedb,0x3f6a3f273f7f3ec4,0x3efc3f7a3f3e3f5c,
0x3f58be893f22bf0e,0x3f7f3eb83f783d49,0xbf80bea1bf758000,0xbf4abf51bf71bf18,0xbe2fbf7ebef1bf7b,0x3ee6bf393e16bf67,0xbecf3f42bdc93f6d,0xbf5f3e60bf2c3f04,
0x3f183f673f553f35,0xbd493f783e953f7f,0xbf5cbf2cbf7bbec4,0xbeacbf7dbf22bf62,0xbe163f713e483f80,0xbf3e3f04bef13f46,0xbe79bf80bf0ebf6d,0x3edbbf4e3dc9bf75,
0xbf4e3edbbf0e3f35,0xbf80be79bf753dc9,0x3f04bf3e3e48bf6d,0x3f71be163f46bef1,0xbf7dbeacbf7b8000,0xbf2cbf5cbf62bf22,0x3f78bd493f55bec4,0x3f673f183f7f3e95,
0xbea1bf7abf22bf55,0x3ecfbf5f3d49bf7d,0x3dfb3f803ef13f6d,0xbf133f42be793f71,0x3d97bf7cbe95bf7b,0x3f39bf1d3edbbf5c,0xbe893f6f3dc93f80,0xbf583ee6bf183f3e,
0x3f73be603f46bf0e,0x3f6a3efc3f803e16,0xbf7e3cc9bf623ec4,0xbf51bf27bf78beac,0x3f7f3e2f3f75be48,0x3f313f4a3f673f04,0xbf77beb8bf7f8000,0xbf09bf65bf4ebf2c,
0xbec43f6d00003f80,0xbf6d3ec4bf353f35,0x3ec4bf6d0000bf80,0x3f6dbec43f35bf35,0xbec43f6d00003f80,0xbf6d3ec4bf353f35,0x3ec4bf6d0000bf80,0x3f6dbec43f35bf35,
0xbf6dbec4bf808000,0xbec4bf6dbf35bf35,0x3f6d3ec43f808000,0x3ec43f6d3f353f35,0xbf6dbec4bf808000,0xbec4bf6dbf35bf35,0x3f6d3ec43f808000,0x3ec43f6d3f353f35,
0x3f27bf513e95bf7b,0x3f80bdfb3f67bf04,0xbefc3f6abdc93f80,0xbf7a3ea1bf4e3f2c,0x3f65bf093f22bf55,0x3f6f3e893f80be16,0xbf4a3f31bef13f6d,0xbf7cbd97bf783eac,
0x3f423f133f753e48,0x3cc93f7e3edb3f5c,0xbf5fbecfbf7f8000,0xbe60bf73bf18bf3e,0x3ee63f583f463f0e,0xbeb83f773d493f7d,0xbf1dbf39bf62bec4,0x3e2fbf7fbe79bf71,
0xbf7d3eacbf553f35,0xbf3ebf04bf75bdc9,0x3f783d493f7bbec4,0x3edb3f4e3f463ef1,0xbf183f67be483f80,0xbf803e79bf623f22,0x3f5cbf2c3f0ebf6d,0x3f713e163f7fbe95,
0xbe16bf71bf0ebf35,0x3f2cbf5c3e95bf7f,0xbe793f803e483f6d,0xbf673f18bf223f62,0xbf4ebedbbf7b8000,0xbd49bf78bef1bf46,0x3f043f3e3f553ec4,0xbeac3f7d3dc93f75,
0x3f133f1d3f623e48,0xbea13f803e163f67,0xbf6fbd97bf7f3ec4,0xbe89bf58bf2cbf04,0x3f7abefc3f46bf55,0x3f423ecf3f78bd49,0xbf313f65be953f80,0xbf7e3e2fbf713f18,
0xbf513f4abef13f7b,0xbf73bcc9bf7d3edb,0x3eb8bf7fbdc9bf6d,0x3f77bf093f3ebf5c,0x3e603f5f3f223f0e,0xbf273f6abe793f80,0xbf39bee6bf758000,0x3dfbbf7cbeacbf4e,
0xbf463f62bec43f80,0xbf753dc9bf7b3f0e,0x3f7fbe953f6dbf35,0x3ef13f223f553e48,0xbf22bef1bf6d0000,0x3e95bf7fbe48bf55,0xbdc93f753ec43f35,0xbf623f46bf0e3f7b,
0xbf22bef1bf6d8000,0x3e95bf7fbe48bf55,0xbdc93f753ec43f35,0xbf623f46bf0e3f7b,0x3f46bf623ec4bf80,0x3f75bdc93f7bbf0e,0xbf7f3e95bf6d3f35,0xbef1bf22bf55be48,
0x3f6abd973f7fbf0e,0x3dfb3f513f183edb,0xbf583f5fbef13f80,0xbf653cc9bf803f04,0xbf393f73be953f7b,0xbf773e60bf783f2c,0xbe2fbf4abf22bec4,0x3f42bf6f3eacbf7d,
0xbecf3f7f3dc93f55,0xbf7e3f13bf4e3f67,0xbf09befcbf628000,0x3ee6bf80bd49bf5c,0xbf31bea1bf753e48,0x3e89bf7abe79bf3e,0x3f7cbf1d3f46bf6d,0x3f273eb83f71be16,
0x3eacbf78be48bf35,0x3f7dbf2c3f46bf75,0xbf803f18bf553f6d,0xbf04bedbbf623dc9,0xbf673f5cbf0e3f80,0xbf4ebd49bf7f3ef1,0x3f3e3e163f7bbec4,0xbe793f713e953f22,
0x3f71be793f7bbf35,0x3e163f3e3f223e95,0xbd49bf4ebf0ebec4,0x3f5cbf673ef1bf7f,0xbedbbf04bf558000,0x3f18bf803dc9bf62,0xbf2c3f7dbe483f6d,0xbf783eacbf753f46,
0xbf4a3cc9bf7f3f0e,0x3e60bf65beacbf04,0x3f42bf7c3e95bf6d,0x3f6abe893f7dbf3e,0x3efc3eb83f62be48,0xbf133f7fbd493f4e,0xbf733f58bf223f80,0xbf31bdfbbf783edb,
0x3f1dbf803dc9bf55,0x3f7abee63f71bf5c,0x3f273e2f3f75bec4,0xbecf3f773e163f2c,0xbf5f3f6fbef13f7b,0xbf513d97bf803f18,0xbea1bf09bf468000,0x3f39bf7e3e79bf67,
0xbf7b3f55bf353f80,0xbf0ebe48bf6d3ec4,0x3e483f0e3f350000,0xbf553f7bbec43f6d,0x3f7bbf553f35bf80,0x3f0e3e483f6dbec4,0xbe48bf0ebf350000,0x3f55bf7b3ec4bf6d,
0xbe48bf0ebf358000,0x3f55bf7b3ec4bf6d,0xbf7b3f55bf353f80,0xbf0ebe48bf6d3ec4,0x3e483f0e3f358000,0xbf553f7bbec43f6d,0x3f7bbf553f35bf80,0x3f0e3e483f6dbec4,
0xbdfb3f393ef13e48,0xbf7a3f65bf2c3f7d,0xbf7f3f51bf463f80,0xbecfbe89bf5c3eac,0x3efcbf6fbdc9bf0e,0x3f7cbf273f67bf78,0x3f73bf093f75bf6d,0x3cc93f1d3f183d49,
0xbf7e3f31bf623f7b,0xbe60bee6bf3e3e16,0xbd97bf13bf228000,0x3f6abf773f04bf71,0x3f5fbeb83f7fbf55,0xbe2f3f423edb3e79,0xbea13f583e953ec4,0xbf803f4abf4e3f80,
0x3f2cbe163f7bbf35,0xbf043f673dc93ef1,0x3f71bf783f0ebf6d,0x3f18bd493f75bf22,0xbf803f4ebf553f80,0xbe79beacbf463e95,0xbedb3f5c3e483ec4,0xbf7d3f3ebf623f7f,
0xbf3e3f7dbe483f35,0xbf5c3edbbf7f3f62,0x3eac3e793f55bec4,0xbf4e3f80be953f46,0x3d49bf18bf0e8000,0x3f78bf713f22bf75,0xbf673f04bf7b3f6d,0x3e16bf2cbef1bdc9,
0x3f6fbf273f75bf7b,0xbdfb3f133f04bd49,0x3e603e893f46bec4,0xbf653f80bedb3f4e,0xbf313f73bdc93f0e,0xbf5f3f09bf7d3f71,0xbf7c3f4abf623f80,0xbd97becfbf2c3e79,
0xbeb83f423e953e48,0xbf7e3f51bf5c3f80,0xbf7a3f77bf223f6d,0xbee6bcc9bf673f18,0xbf393ea1bf7f3f55,0x3efcbf58be16beac,0x3e2fbf1dbef18000,0x3f7fbf6a3f3ebf78,
0xbf753f46bf6d3f80,0x3dc9bef1bf0e3e48,0xbf623f7fbec43f35,0xbf223e95bf7b3f55,0xbe953f223ec40000,0xbf7f3f62bf553f7b,0x3ef1bdc93f6dbf35,0xbf463f75be483f0e,
0x3e95bf22bec48000,0x3f7fbf623f55bf7b,0xbef13dc9bf6d3f35,0x3f46bf753e48bf0e,0xbf753f46bf6d3f80,0x3dc9bef1bf0e3e48,0xbf623f7fbec43f35,0xbf223e95bf7b3f55,
0xbf7c3f7ebf223f55,0xbea13cc9bf5c3f2c,0xbf6a3f42bf753f80,0x3e89bf09bedb3e16,0xbe603efc3ef1be48,0xbf7f3f6fbf4e3f71,0xbf393f65bdc93ec4,0xbf4a3f13bf803f78,
0xbe2fbdfbbf463f0e,0x3f73bf803f04bf3e,0x3ecfbf27be958000,0x3f77bf583f67bf7d,0xbf7a3f5fbf623f7b,0x3d97beb8bf183eac,0xbf313ee6bf7f3f6d,0x3f1dbf51bd49be79,
0xbf783f80bf0e3f35,0xbeac3e16bf623f46,0xbf4e3f67be483ec4,0xbf2c3f04bf7f3f75,0xbf5c3f3ebf7b3f80,0x3edbbf18be953dc9,0xbf7d3f71bf553f6d,0x3d49be79bf223ef1,
0xbe793d49bf553f35,0x3f71bf7d3ef1bf22,0xbf183edbbf7b3f6d,0x3f3ebf5c3dc9be95,0x3f04bf2cbe488000,0x3f67bf4e3f75bf7f,0x3e16beacbf0e3ec4,0x3f80bf783f46bf62,
0xbf7f3f7cbf463f55,0x3cc9bdfbbf2c3f18,0xbf773f6fbf623f6d,0x3e60bea1bf043edb,0xbf653f58bf753f7b,0x3ecfbefcbeac3e79,0xbf4a3f39bf7f3f80,0x3f13bf27be163d49,
0x3d97be2fbf223f0e,0x3f80bf7e3f3ebf4e,0x3e89beb8bef13ec4,0x3f7abf733f5cbf67,0x3ee6bf09be953e48,0x3f6abf5f3f71bf78,0x3f1dbf31bdc98000,0x3f51bf423f7dbf80,
0x3f003f003f003f00,0x3f003f003f003f00,0x3f003f003f003f00,0x3f003f003f003f00,0x3f003f003f003f00,0x3f003f003f003f00,0x3f003f003f003f00,0x3f003f003f003f00,
0xbf00bf003f003f00,0xbf00bf003f003f00,0xbf00bf003f003f00,0xbf00bf003f003f00,0xbf00bf003f003f00,0xbf00bf003f003f00,0xbf00bf003f003f00,0xbf00bf003f003f00,
0x3ee63f093ef13f0e,0x3ecf3efc3edb3f04,0x3f1d3f313f223f35,0x3f133f273f183f2c,0x3d973e2f3dc93e48,0x3cc93dfb3d493e16,0x3e893eb83e953ec4,0x3e603ea13e793eac,
0xbf65bf58bf62bf55,0xbf6abf5fbf67bf5c,0xbf4abf39bf46bf35,0xbf51bf42bf4ebf3e,0xbf7fbf7cbf7fbf7b,0xbf80bf7ebf80bf7d,0xbf77bf6fbf75bf6d,0xbf7abf73bf78bf71,
0xbf5cbf3ebf55bf35,0xbf67bf4ebf62bf46,0xbf7dbf71bf7bbf6d,0xbf80bf78bf7fbf75,0xbe79bd49be480000,0xbeacbe16be95bdc9,0xbf18bedbbf0ebec4,0xbf2cbf04bf22bef1,
0xbf04bf2cbf0ebf35,0xbedbbf18bef1bf22,0xbe16beacbe48bec4,0xbd49be79bdc9be95,0xbf78bf80bf7bbf80,0xbf71bf7dbf75bf7f,0xbf4ebf67bf55bf6d,0xbf3ebf5cbf46bf62,
0xbe60befcbe95bf0e,0xbd97beb8be16bedb,0xbf39bf65bf46bf6d,0xbf1dbf51bf2cbf5c,0xbf7cbf7ebf7fbf7b,0xbf73bf80bf78bf80,0xbf6abf42bf62bf35,0xbf77bf58bf71bf4e,
0x3f7a3f5f3f753f55,0x3f7f3f6f3f7d3f67,0x3f313ee63f223ec4,0x3f4a3f133f3e3f04,0x3e2fbdfb3dc9be48,0x3ea13cc93e79bd49,0xbecfbf27bef1bf35,0xbe89bf09beacbf18,
0xbf62bf7fbf6dbf80,0xbf46bf75bf55bf7b,0xbe95bf22bec4bf35,0xbdc9bef1be48bf0e,0x3ef13dc93ec40000,0x3f223e953f0e3e48,0x3f753f463f6d3f35,0x3f7f3f623f7b3f55,
0x3ef13dc93ec48000,0x3f223e953f0e3e48,0x3f753f463f6d3f35,0x3f7f3f623f7b3f55,0x3f623f7f3f6d3f80,0x3f463f753f553f7b,0x3e953f223ec43f35,0x3dc93ef13e483f0e,
0x3f393ea13f223e48,0x3f5f3f093f4e3edb,0xbe2fbf1dbe95bf35,0x3d97becfbd49bf04,0x3eb83f423ef13f55,0x3dfb3f133e793f2c,0x3f7a3f773f7f3f6d,0x3f653f803f713f7d,
0x3f313f733f463f7b,0x3efc3f583f183f67,0x3f7c3f4a3f753f35,0x3f7f3f6a3f803f5c,0xbf6fbf27bf62bf0e,0xbf7ebf51bf78bf3e,0xbe603e89bdc93ec4,0xbee63cc9beac3e16,
0x3d493f183e483f35,0xbe793eacbdc93ef1,0xbf67bf04bf55bec4,0xbf7dbf3ebf75bf22,0x3f2c3e163f0e0000,0x3f5c3edb3f463e95,0x3f713f783f7b3f6d,0x3f4e3f803f623f7f,
0xbf80bf4ebf7bbf35,0xbf78bf71bf7fbf62,0xbedbbf5cbf0ebf6d,0xbe16bf2cbe95bf46,0x3f3e3f7d3f553f80,0x3f043f673f223f75,0xbeac3e79be483ec4,0xbf18bd49bef13dc9,
0xbefcbf6fbf22bf7b,0xbe2fbf42beacbf5c,0xbf73bf09bf62bec4,0xbf80bf4abf7dbf2c,0x3dfb3f393e953f55,0xbe603ee6bd493f18,0x3f7f3f513f7f3f35,0x3f6a3f773f783f67,
0x3f5f3eb83f463e48,0x3f7c3f273f713f04,0xbea1bf58bef1bf6d,0x3cc9bf1dbe16bf3e,0xbf7ebf31bf75bf0e,0xbf7abf65bf80bf4e,0xbd973f133dc93f35,0xbecf3e89be793edb,
0x3f0e3f7b3f353f80,0x3e483f553ec43f6d,0xbf55be48bf350000,0xbf7bbf0ebf6dbec4,0xbf0ebf7bbf35bf80,0xbe48bf55bec4bf6d,0x3f553e483f350000,0x3f7b3f0e3f6d3ec4,
0xbf55be48bf358000,0xbf7bbf0ebf6dbec4,0xbf0ebf7bbf35bf80,0xbe48bf55bec4bf6d,0x3f553e483f358000,0x3f7b3f0e3f6d3ec4,0x3f0e3f7b3f353f80,0x3e483f553ec43f6d,
0xbf5fbf6fbf75bf55,0xbf13bf7fbf3ebf7d,0xbea13f09bdc93f35,0xbf313dfbbf043eac,0x3f1d3f803f463f7b,0x3e603f653edb3f78,0x3f27be2f3ef1bec4,0x3f6a3e893f4e3d49,
0x3efcbeb83e95bf0e,0x3f513d973f2cbe16,0xbf73bf58bf7fbf35,0xbf39bf7ebf5cbf71,0xbf4abcc9bf223e48,0xbf7abee6bf67be79,0x3f423f7c3f623f6d,0x3ecf3f773f183f80,
0x3f673f5c3f7b3f35,0x3f183f803f463f75,0xbf3e3e16bf0e3ec4,0xbf78beacbf62bdc9,0xbf71be79bf550000,0xbf7dbf2cbf7fbef1,0x3d49bf4ebe48bf6d,0x3f04bedb3e95bf22,
0xbedb3f04be483f35,0xbf4e3d49bf223e95,0xbf2cbf7dbf55bf6d,0xbe79bf71bef1bf7f,0xbeacbf78bf0ebf80,0x3e16bf3ebdc9bf62,0x3f803f183f7b3ec4,0x3f5c3f673f753f46,
0xbf39bf73bf62bf55,0xbe89bf7abf04bf80,0xbe2f3f4a3dc93f6d,0xbf273eb8bedb3f18,0x3f6a3d973f46be48,0x3f7e3f133f7d3eac,0xbf58bf5fbf75bf35,0xbee6bf80bf2cbf78,
0x3f31bea13ef1bf0e,0x3f773e603f5cbd49,0xbf7cbf1dbf7fbec4,0xbf42bf6fbf67bf4e,0x3ecf3f7f3f223f7b,0xbdfb3f513e163f71,0x3f09befc3e95bf35,0x3f653cc93f3ebe79,
0xbdc9bf75bec4bf80,0x3ef1bf223e48bf55,0x3f463f623f6d3f35,0x3e953f7f3f0e3f7b,0xbf7fbe95bf6d0000,0xbf62bf46bf7bbf0e,0x3f22bef13ec4bf35,0x3f753dc93f55be48,
0x3f7f3e953f6d8000,0x3f623f463f7b3f0e,0xbf223ef1bec43f35,0xbf75bdc9bf553e48,0xbdc9bf75bec4bf80,0x3ef1bf223e48bf55,0x3f463f623f6d3f35,0x3e953f7f3f0e3f7b,
0xbe603f5f3dc93f7b,0xbf423ecfbf043f2c,0x3f39bee63ef1bf35,0x3f7e3e2f3f67be16,0x3f513f4a3f753f0e,0x3ea13f803f183f71,0xbeb8bf7fbf22bf6d,0x3e89bf58bd49bf78,
0xbf7abefcbf7fbe48,0xbf27bf6abf5cbf3e,0x3f313f653f623f35,0x3dfb3f7c3edb3f7d,0xbf133f1dbe953f55,0xbf733cc9bf4e3eac,0x3f6fbd973f46bec4,0x3f773f093f803e79,
0x3f4ebedb3f0ebf35,0x3f803e793f75bdc9,0xbf043f3ebe483f6d,0xbf713e16bf463ef1,0x3f7d3eac3f7b0000,0x3f2c3f5c3f623f22,0xbf783d49bf553ec4,0xbf67bf18bf7fbe95,
0x3f183f673f553f35,0xbd493f783e953f7f,0xbf5cbf2cbf7bbec4,0xbeacbf7dbf22bf62,0xbe163f713e483f80,0xbf3e3f04bef13f46,0xbe79bf80bf0ebf6d,0x3edbbf4e3dc9bf75,
0xbf65bf09bf7fbe48,0xbeb8bf77bf2cbf4e,0x3f4a3f313f753ec4,0x3e2f3f7f3f043f67,0xbf27bf51bf62bf0e,0x3cc9bf7ebeacbf78,0x3efc3f6a3f463f35,0xbe603f733e163f80,
0x3ee6bf583dc9bf7b,0x3f6fbe893f3ebf18,0xbf1d3f39be953f6d,0xbf7c3d97bf5c3edb,0x3f42bf133ef1bf55,0x3f803dfb3f71be79,0xbf5f3ecfbf223f35,0xbf7abea1bf7d3d49,
0xbec43f6d00003f80,0xbf6d3ec4bf353f35,0x3ec4bf6d0000bf80,0x3f6dbec43f35bf35,0xbec43f6d00003f80,0xbf6d3ec4bf353f35,0x3ec4bf6d0000bf80,0x3f6dbec43f35bf35,
0xbf6dbec4bf808000,0xbec4bf6dbf35bf35,0x3f6d3ec43f808000,0x3ec43f6d3f353f35,0xbf6dbec4bf808000,0xbec4bf6dbf35bf35,0x3f6d3ec43f808000,0x3ec43f6d3f353f35,
0x3f7fbe2f3f62bf0e,0x3f393f1d3f713e79,0xbf773eb8bf463f35,0xbf58bee6bf7dbd49,0x3f733e603f7fbe48,0x3ecf3f5f3f3e3f18,0xbf7ebcc9bf753ec4,0xbf13bf42bf5cbedb,
0x3d973f7c3ef13f55,0xbf313f4abeac3f78,0xbe89bf6fbf22bf35,0x3f09bf653e16bf80,0xbea13f7a3dc93f7b,0xbf6a3efcbf2c3f4e,0x3dfbbf80be95bf6d,0x3f51bf273f04bf67,
0xbe16bf71bf0ebf35,0x3f2cbf5c3e95bf7f,0xbe793f803e483f6d,0xbf673f18bf223f62,0xbf4ebedbbf7b0000,0xbd49bf78bef1bf46,0x3f043f3e3f553ec4,0xbeac3f7d3dc93f75,
0x3f7dbeac3f55bf35,0x3f3e3f043f753dc9,0xbf78bd49bf7b3ec4,0xbedbbf4ebf46bef1,0x3f18bf673e48bf80,0x3f80be793f62bf22,0xbf5c3f2cbf0e3f6d,0xbf71be16bf7f3e95,
0xbf7c3dfbbf753f0e,0xbee6bf39bf4ebeac,0x3f6abf273f22bf6d,0x3f5f3e603f80be79,0xbf093f77bdc93f7b,0xbf7f3eb8bf5c3f3e,0xbcc9bf73bef1bf35,0x3f4abf513edbbf7d,
0x3e2fbf7ebe95bf55,0x3f65bf313f18bf71,0x3ecf3f423f463ec4,0xbefc3f7abd493f78,0xbf58be89bf7f3e48,0xbd97bf6fbf04bf2c,0x3f80bea13f62bf35,0x3f1d3f133f673e16,
0x3f46bf623ec4bf80,0x3f75bdc93f7bbf0e,0xbf7f3e95bf6d3f35,0xbef1bf22bf55be48,0x3f223ef13f6d0000,0xbe953f7f3e483f55,0x3dc9bf75bec4bf35,0x3f62bf463f0ebf7b,
0x3f223ef13f6d8000,0xbe953f7f3e483f55,0x3dc9bf75bec4bf35,0x3f62bf463f0ebf7b,0xbf463f62bec43f80,0xbf753dc9bf7b3f0e,0x3f7fbe953f6dbf35,0x3ef13f223f553e48,
0xbeb8bf27bf46be48,0x3f1dbf7c3e16bf71,0x3f7abe893f75bf35,0x3ea13f313f3e3e79,0x3f80bee63f62bf55,0x3efc3f093f5c3d49,0xbf133f7ebdc93f6d,0xbf7f3ecfbf673f4e,
0x3f6fbf423f22bf7b,0x3f4a3e2f3f7dbeac,0xbe603f773e953f35,0xbf733f39bf2c3f78,0xbcc93f653ef13f0e,0xbf5f3f58bf043f80,0xbf51bdfbbf7f3ec4,0x3d97bf6abedbbf18,
0xbf713e79bf7b3f35,0xbe16bf3ebf22be95,0x3d493f4e3f0e3ec4,0xbf5c3f67bef13f7f,0x3edb3f043f550000,0xbf183f80bdc93f62,0x3f2cbf7d3e48bf6d,0x3f78beac3f75bf46,
0x3eacbf78be48bf35,0x3f7dbf2c3f46bf75,0xbf803f18bf553f6d,0xbf04bedbbf623dc9,0xbf673f5cbf0e3f80,0xbf4ebd49bf7f3ef1,0x3f3e3e163f7bbec4,0xbe793f713e953f22,
0xbf7e3f39bf463f7b,0xbf09bea1bf673e79,0x3d97bf51bef1bec4,0x3f6fbf5f3f18bf80,0x3f77becf3f75bf55,0x3e2f3f273f2c3e16,0xbee63f7a3dc93f35,0xbf803f1dbf5c3f71,
0xbdfbbf31bf22be48,0x3f58bf733edbbf78,0x3f7fbf133f62bf6d,0x3eb83efc3f4ebd49,0xbe893f6a3e953f0e,0xbf7c3f42bf3e3f7d,0xbf653e60bf7f3f35,0x3cc9bf4abf04beac,
0xbf7b3f55bf353f80,0xbf0ebe48bf6d3ec4,0x3e483f0e3f350000,0xbf553f7bbec43f6d,0x3f7bbf553f35bf80,0x3f0e3e483f6dbec4,0xbe48bf0ebf350000,0x3f55bf7b3ec4bf6d,
0xbe48bf0ebf358000,0x3f55bf7b3ec4bf6d,0xbf7b3f55bf353f80,0xbf0ebe48bf6d3ec4,0x3e483f0e3f358000,0xbf553f7bbec43f6d,0x3f7bbf553f35bf80,0x3f0e3e483f6dbec4,
0xbf4a3f80be953f55,0xbf583ea1bf803f4e,0xbf423e2fbf7f3f35,0x3eb8bf5fbe79bedb,0x3f77bf6a3f22bf7b,0x3f133d973f71bf04,0x3ee63e603f62bec4,0xbf313f7ebe163f3e,
0xbf1dbcc9bf753f0e,0x3f09bf73bd49bf18,0x3f27bf7c3dc9bf35,0x3f6fbefc3f78bf67,0x3e893ecf3f46be48,0xbf513f7fbeac3f5c,0xbf653f7abef13f6d,0xbf393dfbbf7d3f2c,
0xbf3e3f7dbe483f35,0xbf5c3edbbf7f3f62,0x3eac3e793f55bec4,0xbf4e3f80be953f46,0x3d49bf18bf0e0000,0x3f78bf713f22bf75,0xbf673f04bf7b3f6d,0x3e16bf2cbef1bdc9,
0xbf2c3e16bf7b3f35,0x3f04bf67bdc9bef1,0xbf713f78bf0e3f6d,0xbf183d49bf753f22,0x3f80bf4e3f55bf80,0x3e793eac3f46be95,0x3edbbf5cbe48bec4,0x3f7dbf3e3f62bf7f,
0xbf6a3f7fbef13f55,0xbf1d3e2fbf783f3e,0xbf583efcbf7f3f6d,0x3ea1bf39beacbe16,0xbcc9bee6bf223e48,0x3f77bf7a3f18bf67,0x3f51bf7e3e95bf35,0x3f42beb83f80bf5c,
0xbecfbd97bf623f0e,0x3f4abf7c3e79bf2c,0x3f09bf5fbdc9bec4,0x3f73bf313f71bf7d,0x3f80bf653f46bf7b,0x3e893e603f4ebedb,0x3f13bdfb3f75bf35,0xbf273f6fbd493f04,
0x3f75bf463f6dbf80,0xbdc93ef13f0ebe48,0x3f62bf7f3ec4bf35,0x3f22be953f7bbf55,0x3e95bf22bec40000,0x3f7fbf623f55bf7b,0xbef13dc9bf6d3f35,0x3f46bf753e48bf0e,
0xbe953f223ec48000,0xbf7f3f62bf553f7b,0x3ef1bdc93f6dbf35,0xbf463f75be483f0e,0x3f75bf463f6dbf80,0xbdc93ef13f0ebe48,0x3f62bf7f3ec4bf35,0x3f22be953f7bbf55,
0x3f51bf1d3f7fbf7b,0xbee63f313e793d49,0x3eb8bd973f62bf35,0xbf5f3f7abeac3f18,0x3f58bf773e95bf0e,0x3f27becf3f7dbf67,0x3f80bf733f46bf6d,0x3dfb3e2f3f3ebf04,
0xbf133f4a3dc93e48,0xbf653f39bf783f80,0xbf6f3f7fbef13f35,0xbefc3e60bf713f4e,0x3f09be893f75bf55,0xbf423f6abe163edb,0xbcc93ea13f22bec4,0xbf7e3f7cbf2c3f5c,
0x3e79bd493f55bf35,0xbf713f7dbef13f22,0x3f18bedb3f7bbf6d,0xbf3e3f5cbdc93e95,0xbf043f2c3e480000,0xbf673f4ebf753f7f,0xbe163eac3f0ebec4,0xbf803f78bf463f62,
0xbf783f80bf0e3f35,0xbeac3e16bf623f46,0xbf4e3f67be483ec4,0xbf2c3f04bf7f3f75,0xbf5c3f3ebf7b3f80,0x3edbbf18be953dc9,0xbf7d3f71bf553f6d,0x3d49be79bf223ef1,
0xbf423f51bdc93e48,0xbf313f1dbf803f7d,0xbf5f3f6abe953ec4,0xbf093ee6bf783f71,0xbf733f7abef13f0e,0xbeb83e89bf673f5c,0xbf7e3f80bf223f35,0xbe2f3d97bf4e3f3e,
0xbf273f13bf7f3f7b,0x3f39bf4a3d49be16,0xbefc3ecfbf753f6d,0x3f58bf653e79beac,0xbea13e60bf623f55,0x3f6fbf773edbbf04,0xbdfb3cc9bf463f35,0x3f7cbf7f3f18bf2c,
0x3f003f003f003f00,0x3f003f003f003f00,0x3f003f003f003f00,0x3f003f003f003f00,0x3f003f003f003f00,0x3f003f003f003f00,0x3f003f003f003f00,0x3f003f003f003f00,
0xbf00bf003f003f00,0xbf00bf003f003f00,0xbf00bf003f003f00,0xbf00bf003f003f00,0xbf00bf003f003f00,0xbf00bf003f003f00,0xbf00bf003f003f00,0xbf00bf003f003f00,
0xbea1be60be95be48,0xbeb8be89beacbe79,0xbdfbbcc9bdc90000,0xbe2fbd97be16bd49,0xbf27bf13bf22bf0e,0xbf31bf1dbf2cbf18,0xbefcbecfbef1bec4,0xbf09bee6bf04bedb,
0xbf73bf7abf75bf7b,0xbf6fbf77bf71bf78,0xbf7ebf80bf7fbf80,0xbf7cbf7fbf7dbf80,0xbf42bf51bf46bf55,0xbf39bf4abf3ebf4e,0xbf5fbf6abf62bf6d,0xbf58bf65bf5cbf67,
0xbf04bf2cbf0ebf35,0xbedbbf18bef1bf22,0xbe16beacbe48bec4,0xbd49be79bdc9be95,0xbf78bf80bf7bbf80,0xbf71bf7dbf75bf7f,0xbf4ebf67bf55bf6d,0xbf3ebf5cbf46bf62,
0x3f5c3f3e3f553f35,0x3f673f4e3f623f46,0x3f7d3f713f7b3f6d,0x3f803f783f7f3f75,0x3e793d493e488000,0x3eac3e163e953dc9,0x3f183edb3f0e3ec4,0x3f2c3f043f223ef1,
0x3f583f773f623f7b,0x3f423f6a3f4e3f71,0x3f803f733f7f3f6d,0x3f7e3f7c3f803f78,0x3f513f1d3f463f0e,0x3f653f393f5c3f2c,0x3eb83d973e950000,0x3efc3e603edb3e16,
0xbf09be89bef1be48,0xbf27becfbf18beac,0x3cc93ea13dc93ec4,0xbdfb3e2fbd493e79,0x3f133f4a3f223f55,0x3ee63f313f043f3e,0x3f6f3f7f3f753f80,0x3f5f3f7a3f673f7d,
0x3f623f7f3f6d3f80,0x3f463f753f553f7b,0x3e953f223ec43f35,0x3dc93ef13e483f0e,0xbef1bdc9bec40000,0xbf22be95bf0ebe48,0xbf75bf46bf6dbf35,0xbf7fbf62bf7bbf55,
0xbef1bdc9bec48000,0xbf22be95bf0ebe48,0xbf75bf46bf6dbf35,0xbf7fbf62bf7bbf55,0xbf62bf7fbf6dbf80,0xbf46bf75bf55bf7b,0xbe95bf22bec4bf35,0xbdc9bef1be48bf0e,
0xbf80bf65bf7fbf55,0xbf77bf7abf7dbf71,0xbf13bdfbbef10000,0xbf42beb8bf2cbe79,0x3ecfbd973e95be48,0x3f1d3e2f3f043d49,0xbf09bf5fbf22bf6d,0xbea1bf39bedbbf4e,
0x3cc9bee6bdc9bf0e,0x3e89be603e16beac,0xbf51bf7ebf62bf80,0xbf27bf6fbf3ebf78,0x3f6a3f7f3f753f7b,0x3f4a3f7c3f5c3f80,0x3f583efc3f463ec4,0x3f733f313f673f18,
0x3f803f4e3f7b3f35,0x3f783f713f7f3f62,0x3edb3f5c3f0e3f6d,0x3e163f2c3e953f46,0xbf3ebf7dbf55bf80,0xbf04bf67bf22bf75,0x3eacbe793e48bec4,0x3f183d493ef1bdc9,
0x3d493f183e483f35,0xbe793eacbdc93ef1,0xbf67bf04bf55bec4,0xbf7dbf3ebf75bf22,0x3f2c3e163f0e8000,0x3f5c3edb3f463e95,0x3f713f783f7b3f6d,0x3f4e3f803f623f7f,
0xbf77bf6abf7fbf55,0xbf51bf7fbf67bf78,0xbee63e60be953ec4,0xbf39bdfbbf183d49,0x3f4a3f803f623f7b,0x3f093f733f2c3f7d,0x3f423e2f3f220000,0x3f6f3efc3f5c3eac,
0x3e89becf3dc9bf0e,0x3f13bd973edbbe79,0xbf65bf7abf75bf6d,0xbf31bf7ebf4ebf80,0xbf1d3cc9bef13e48,0xbf58bea1bf3ebe16,0x3f273f7c3f463f80,0x3eb83f5f3f043f71,
0x3f0e3f7b3f353f80,0x3e483f553ec43f6d,0xbf55be48bf350000,0xbf7bbf0ebf6dbec4,0xbf0ebf7bbf35bf80,0xbe48bf55bec4bf6d,0x3f553e483f350000,0x3f7b3f0e3f6d3ec4,
0xbf55be48bf358000,0xbf7bbf0ebf6dbec4,0xbf0ebf7bbf35bf80,0xbe48bf55bec4bf6d,0x3f553e483f358000,0x3f7b3f0e3f6d3ec4,0x3f0e3f7b3f353f80,0x3e483f553ec43f6d,
0xbe89bf6abef1bf7b,0x3e2fbf27bd49bf4e,0xbf65be60bf460000,0xbf80bf1dbf78bedb,0xbdfb3f313dc93f55,0xbf093ea1beac3f04,0x3f7f3f133f753ec4,0x3f6f3f5f3f7d3f3e,
0x3f773ecf3f623e48,0x3f7c3f423f803f18,0xbee6bf7abf22bf80,0xbcc9bf4abe79bf67,0xbf7ebf39bf7fbf0e,0xbf58bf73bf71bf5c,0x3d973f513e953f6d,0xbeb83efcbe163f2c,
0xbedb3f04be483f35,0xbf4e3d49bf223e95,0xbf2cbf7dbf55bf6d,0xbe79bf71bef1bf7f,0xbeacbf78bf0ebf80,0x3e16bf3ebdc9bf62,0x3f803f183f7b3ec4,0x3f5c3f673f753f46,
0xbf67bf5cbf7bbf35,0xbf18bf80bf46bf75,0x3f3ebe163f0ebec4,0x3f783eac3f623dc9,0x3f713e793f558000,0x3f7d3f2c3f7f3ef1,0xbd493f4e3e483f6d,0xbf043edbbe953f22,
0x3f803ee63f753e48,0x3f5f3f583f783f2c,0xbf13bf7ebf46bf6d,0xbd97bf6abeacbf7d,0xbeb83f27bdc93f55,0xbf4a3e2fbf183edb,0x3f7a3e893f620000,0x3f733f393f803f04,
0x3cc93f653e953f7b,0xbefc3f09be793f3e,0x3f51bdfb3f22bec4,0x3f7f3ecf3f713e16,0xbf6fbf42bf7fbf0e,0xbf1dbf7cbf4ebf67,0x3e603f773ef13f80,0xbea13f31bd493f5c,
0x3dc93f753ec43f80,0xbef13f22be483f55,0xbf46bf62bf6dbf35,0xbe95bf7fbf0ebf7b,0x3f7f3e953f6d0000,0x3f623f463f7b3f0e,0xbf223ef1bec43f35,0xbf75bdc9bf553e48,
0xbf7fbe95bf6d8000,0xbf62bf46bf7bbf0e,0x3f22bef13ec4bf35,0x3f753dc93f55be48,0x3dc93f753ec43f80,0xbef13f22be483f55,0xbf46bf62bf6dbf35,0xbe95bf7fbf0ebf7b,
0x3f58be893f22bf0e,0x3f7f3eb83f783d49,0xbf80bea1bf750000,0xbf4abf51bf71bf18,0xbe2fbf7ebef1bf7b,0x3ee6bf393e16bf67,0xbecf3f42bdc93f6d,0xbf5f3e60bf2c3f04,
0x3f093f773f463f55,0xbd973f6f3e793f80,0x3cc9bf73be95bf80,0x3f1dbf133eacbf4e,0x3f7c3dfb3f62be48,0x3f653f313f7d3edb,0xbf6abf27bf7fbec4,0xbefcbf7abf3ebf5c,
0xbf18bf67bf55bf35,0x3d49bf78be95bf7f,0x3f5c3f2c3f7b3ec4,0x3eac3f7d3f223f62,0x3e16bf71be48bf80,0x3f3ebf043ef1bf46,0x3e793f803f0e3f6d,0xbedb3f4ebdc93f75,
0x3f4ebedb3f0ebf35,0x3f803e793f75bdc9,0xbf043f3ebe483f6d,0xbf713e16bf463ef1,0x3f7d3eac3f7b8000,0x3f2c3f5c3f623f22,0xbf783d49bf553ec4,0xbf67bf18bf7fbe95,
0xbf733e60bf463f0e,0xbf6abefcbf80be16,0x3f7ebcc93f62bec4,0x3f513f273f783eac,0xbf7fbe2fbf753e48,0xbf31bf4abf67bf04,0x3f773eb83f7f0000,0x3f093f653f4e3f2c,
0xbea1bf7abf22bf55,0x3ecfbf5f3d49bf7d,0x3dfb3f803ef13f6d,0xbf133f42be793f71,0x3d97bf7cbe95bf7b,0x3f39bf1d3edbbf5c,0xbe893f6f3dc93f80,0xbf583ee6bf183f3e,
0xbec43f6d00003f80,0xbf6d3ec4bf353f35,0x3ec4bf6d0000bf80,0x3f6dbec43f35bf35,0xbec43f6d00003f80,0xbf6d3ec4bf353f35,0x3ec4bf6d0000bf80,0x3f6dbec43f35bf35,
0xbf6dbec4bf808000,0xbec4bf6dbf35bf35,0x3f6d3ec43f808000,0x3ec43f6d3f353f35,0xbf6dbec4bf808000,0xbec4bf6dbf35bf35,0x3f6d3ec43f808000,0x3ec43f6d3f353f35,
0x3f423f133f753e48,0x3cc93f7e3edb3f5c,0xbf5fbecfbf7f0000,0xbe60bf73bf18bf3e,0x3ee63f583f463f0e,0xbeb83f773d493f7d,0xbf1dbf39bf62bec4,0x3e2fbf7fbe79bf71,
0xbf273f51be953f7b,0xbf803dfbbf673f04,0x3efcbf6a3dc9bf80,0x3f7abea13f4ebf2c,0xbf653f09bf223f55,0xbf6fbe89bf803e16,0x3f4abf313ef1bf6d,0x3f7c3d973f78beac,
0x3f7dbeac3f55bf35,0x3f3e3f043f753dc9,0xbf78bd49bf7b3ec4,0xbedbbf4ebf46bef1,0x3f18bf673e48bf80,0x3f80be793f62bf22,0xbf5c3f2cbf0e3f6d,0xbf71be16bf7f3e95,
0x3e163f713f0e3f35,0xbf2c3f5cbe953f7f,0x3e79bf80be48bf6d,0x3f67bf183f22bf62,0x3f4e3edb3f7b8000,0x3d493f783ef13f46,0xbf04bf3ebf55bec4,0x3eacbf7dbdc9bf75,
0x3f51bf4a3ef1bf7b,0x3f733cc93f7dbedb,0xbeb83f7f3dc93f6d,0xbf773f09bf3e3f5c,0xbe60bf5fbf22bf0e,0x3f27bf6a3e79bf80,0x3f393ee63f750000,0xbdfb3f7c3eac3f4e,
0x3f133f1d3f623e48,0xbea13f803e163f67,0xbf6fbd97bf7f3ec4,0xbe89bf58bf2cbf04,0x3f7abefc3f46bf55,0x3f423ecf3f78bd49,0xbf313f65be953f80,0xbf7e3e2fbf713f18,
0xbf463f62bec43f80,0xbf753dc9bf7b3f0e,0x3f7fbe953f6dbf35,0x3ef13f223f553e48,0xbf22bef1bf6d0000,0x3e95bf7fbe48bf55,0xbdc93f753ec43f35,0xbf623f46bf0e3f7b,
0xbf22bef1bf6d8000,0x3e95bf7fbe48bf55,0xbdc93f753ec43f35,0xbf623f46bf0e3f7b,0x3f46bf623ec4bf80,0x3f75bdc93f7bbf0e,0xbf7f3e95bf6d3f35,0xbef1bf22bf55be48,
0xbecf3f7f3dc93f55,0xbf7e3f13bf4e3f67,0xbf09befcbf620000,0x3ee6bf80bd49bf5c,0xbf31bea1bf753e48,0x3e89bf7abe79bf3e,0x3f7cbf1d3f46bf6d,0x3f273eb83f71be16,
0xbf6a3d97bf7f3f0e,0xbdfbbf51bf18bedb,0x3f58bf5f3ef1bf80,0x3f65bcc93f80bf04,0x3f39bf733e95bf7b,0x3f77be603f78bf2c,0x3e2f3f4a3f223ec4,0xbf423f6fbeac3f7d,
0xbeac3f783e483f35,0xbf7d3f2cbf463f75,0x3f80bf183f55bf6d,0x3f043edb3f62bdc9,0x3f67bf5c3f0ebf80,0x3f4e3d493f7fbef1,0xbf3ebe16bf7b3ec4,0x3e79bf71be95bf22,
0xbf713e79bf7b3f35,0xbe16bf3ebf22be95,0x3d493f4e3f0e3ec4,0xbf5c3f67bef13f7f,0x3edb3f043f558000,0xbf183f80bdc93f62,0x3f2cbf7d3e48bf6d,0x3f78beac3f75bf46,
0xbf1d3f80bdc93f55,0xbf7a3ee6bf713f5c,0xbf27be2fbf753ec4,0x3ecfbf77be16bf2c,0x3f5fbf6f3ef1bf7b,0x3f51bd973f80bf18,0x3ea13f093f460000,0xbf393f7ebe793f67,
0xbf4a3cc9bf7f3f0e,0x3e60bf65beacbf04,0x3f42bf7c3e95bf6d,0x3f6abe893f7dbf3e,0x3efc3eb83f62be48,0xbf133f7fbd493f4e,0xbf733f58bf223f80,0xbf31bdfbbf783edb,
0xbf7b3f55bf353f80,0xbf0ebe48bf6d3ec4,0x3e483f0e3f350000,0xbf553f7bbec43f6d,0x3f7bbf553f35bf80,0x3f0e3e483f6dbec4,0xbe48bf0ebf350000,0x3f55bf7b3ec4bf6d,
0xbe48bf0ebf358000,0x3f55bf7b3ec4bf6d,0xbf7b3f55bf353f80,0xbf0ebe48bf6d3ec4,0x3e483f0e3f358000,0xbf553f7bbec43f6d,0x3f7bbf553f35bf80,0x3f0e3e483f6dbec4,
0xbf7e3f31bf623f7b,0xbe60bee6bf3e3e16,0xbd97bf13bf220000,0x3f6abf773f04bf71,0x3f5fbeb83f7fbf55,0xbe2f3f423edb3e79,0xbea13f583e953ec4,0xbf803f4abf4e3f80,
0x3dfbbf39bef1be48,0x3f7abf653f2cbf7d,0x3f7fbf513f46bf80,0x3ecf3e893f5cbeac,0xbefc3f6f3dc93f0e,0xbf7c3f27bf673f78,0xbf733f09bf753f6d,0xbcc9bf1dbf18bd49,
0xbf2c3e16bf7b3f35,0x3f04bf67bdc9bef1,0xbf713f78bf0e3f6d,0xbf183d49bf753f22,0x3f80bf4e3f55bf80,0x3e793eac3f46be95,0x3edbbf5cbe48bec4,0x3f7dbf3e3f62bf7f,
0x3f3ebf7d3e48bf35,0x3f5cbedb3f7fbf62,0xbeacbe79bf553ec4,0x3f4ebf803e95bf46,0xbd493f183f0e8000,0xbf783f71bf223f75,0x3f67bf043f7bbf6d,0xbe163f2c3ef13dc9,
0x3eb8bf42be95be48,0x3f7ebf513f5cbf80,0x3f7abf773f22bf6d,0x3ee63cc93f67bf18,0x3f39bea13f7fbf55,0xbefc3f583e163eac,0xbe2f3f1d3ef10000,0xbf7f3f6abf3e3f78,
0x3f6fbf273f75bf7b,0xbdfb3f133f04bd49,0x3e603e893f46bec4,0xbf653f80bedb3f4e,0xbf313f73bdc93f0e,0xbf5f3f09bf7d3f71,0xbf7c3f4abf623f80,0xbd97becfbf2c3e79,
0xbf753f46bf6d3f80,0x3dc9bef1bf0e3e48,0xbf623f7fbec43f35,0xbf223e95bf7b3f55,0xbe953f223ec40000,0xbf7f3f62bf553f7b,0x3ef1bdc93f6dbf35,0xbf463f75be483f0e,
0x3e95bf22bec48000,0x3f7fbf623f55bf7b,0xbef13dc9bf6d3f35,0x3f46bf753e48bf0e,0xbf753f46bf6d3f80,0x3dc9bef1bf0e3e48,0xbf623f7fbec43f35,0xbf223e95bf7b3f55,
0xbe2fbdfbbf463f0e,0x3f73bf803f04bf3e,0x3ecfbf27be950000,0x3f77bf583f67bf7d,0xbf7a3f5fbf623f7b,0x3d97beb8bf183eac,0xbf313ee6bf7f3f6d,0x3f1dbf51bd49be79,
0x3f7cbf7e3f22bf55,0x3ea1bcc93f5cbf2c,0x3f6abf423f75bf80,0xbe893f093edbbe16,0x3e60befcbef13e48,0x3f7fbf6f3f4ebf71,0x3f39bf653dc9bec4,0x3f4abf133f80bf78,
0x3f78bf803f0ebf35,0x3eacbe163f62bf46,0x3f4ebf673e48bec4,0x3f2cbf043f7fbf75,0x3f5cbf3e3f7bbf80,0xbedb3f183e95bdc9,0x3f7dbf713f55bf6d,0xbd493e793f22bef1,
0x3e79bd493f55bf35,0xbf713f7dbef13f22,0x3f18bedb3f7bbf6d,0xbf3e3f5cbdc93e95,0xbf043f2c3e488000,0xbf673f4ebf753f7f,0xbe163eac3f0ebec4,0xbf803f78bf463f62,
0xbd973e2f3f22bf0e,0xbf803f7ebf3e3f4e,0xbe893eb83ef1bec4,0xbf7a3f73bf5c3f67,0xbee63f093e95be48,0xbf6a3f5fbf713f78,0xbf1d3f313dc90000,0xbf513f42bf7d3f80,
0xbf7f3f7cbf463f55,0x3cc9bdfbbf2c3f18,0xbf773f6fbf623f6d,0x3e60bea1bf043edb,0xbf653f58bf753f7b,0x3ecfbefcbeac3e79,0xbf4a3f39bf7f3f80,0x3f13bf27be163d49,
0x3f003f003f003f00,0x3f003f003f003f00,0x3f003f003f003f00,0x3f003f003f003f00,0x3f003f003f003f00,0x3f003f003f003f00,0x3f003f003f003f00,0x3f003f003f003f00,
0xbf00bf003f003f00,0xbf00bf003f003f00,0xbf00bf003f003f00,0xbf00bf003f003f00,0xbf00bf003f003f00,0xbf00bf003f003f00,0xbf00bf003f003f00,0xbf00bf003f003f00,
0xbf65bf58bf62bf55,0xbf6abf5fbf67bf5c,0xbf4abf39bf46bf35,0xbf51bf42bf4ebf3e,0xbf7fbf7cbf7fbf7b,0xbf80bf7ebf80bf7d,0xbf77bf6fbf75bf6d,0xbf7abf73bf78bf71,
0xbee6bf09bef1bf0e,0xbecfbefcbedbbf04,0xbf1dbf31bf22bf35,0xbf13bf27bf18bf2c,0xbd97be2fbdc9be48,0xbcc9bdfbbd49be16,0xbe89beb8be95bec4,0xbe60bea1be79beac,
0x3f5c3f3e3f553f35,0x3f673f4e3f623f46,0x3f7d3f713f7b3f6d,0x3f803f783f7f3f75,0x3e793d493e480000,0x3eac3e163e953dc9,0x3f183edb3f0e3ec4,0x3f2c3f043f223ef1,
0x3f043f2c3f0e3f35,0x3edb3f183ef13f22,0x3e163eac3e483ec4,0x3d493e793dc93e95,0x3f783f803f7b3f80,0x3f713f7d3f753f7f,0x3f4e3f673f553f6d,0x3f3e3f5c3f463f62,
0xbf7abf5fbf75bf55,0xbf7fbf6fbf7dbf67,0xbf31bee6bf22bec4,0xbf4abf13bf3ebf04,0xbe2f3dfbbdc93e48,0xbea1bcc9be793d49,0x3ecf3f273ef13f35,0x3e893f093eac3f18,
0xbe60befcbe95bf0e,0xbd97beb8be16bedb,0xbf39bf65bf46bf6d,0xbf1dbf51bf2cbf5c,0xbf7cbf7ebf7fbf7b,0xbf73bf80bf78bf80,0xbf6abf42bf62bf35,0xbf77bf58bf71bf4e,
0xbf62bf7fbf6dbf80,0xbf46bf75bf55bf7b,0xbe95bf22bec4bf35,0xbdc9bef1be48bf0e,0x3ef13dc93ec40000,0x3f223e953f0e3e48,0x3f753f463f6d3f35,0x3f7f3f623f7b3f55,
0x3ef13dc93ec48000,0x3f223e953f0e3e48,0x3f753f463f6d3f35,0x3f7f3f623f7b3f55,0x3f623f7f3f6d3f80,0x3f463f753f553f7b,0x3e953f223ec43f35,0x3dc93ef13e483f0e,
0x3f313f733f463f7b,0x3efc3f583f183f67,0x3f7c3f4a3f753f35,0x3f7f3f6a3f803f5c,0xbf6fbf27bf62bf0e,0xbf7ebf51bf78bf3e,0xbe603e89bdc93ec4,0xbee63cc9beac3e16,
0xbf39bea1bf22be48,0xbf5fbf09bf4ebedb,0x3e2f3f1d3e953f35,0xbd973ecf3d493f04,0xbeb8bf42bef1bf55,0xbdfbbf13be79bf2c,0xbf7abf77bf7fbf6d,0xbf65bf80bf71bf7d,
0xbd49bf18be48bf35,0x3e79beac3dc9bef1,0x3f673f043f553ec4,0x3f7d3f3e3f753f22,0xbf2cbe16bf0e0000,0xbf5cbedbbf46be95,0xbf71bf78bf7bbf6d,0xbf4ebf80bf62bf7f,
0x3f803f4e3f7b3f35,0x3f783f713f7f3f62,0x3edb3f5c3f0e3f6d,0x3e163f2c3e953f46,0xbf3ebf7dbf55bf80,0xbf04bf67bf22bf75,0x3eacbe793e48bec4,0x3f183d493ef1bdc9,
0xbf5fbeb8bf46be48,0xbf7cbf27bf71bf04,0x3ea13f583ef13f6d,0xbcc93f1d3e163f3e,0x3f7e3f313f753f0e,0x3f7a3f653f803f4e,0x3d97bf13bdc9bf35,0x3ecfbe893e79bedb,
0xbefcbf6fbf22bf7b,0xbe2fbf42beacbf5c,0xbf73bf09bf62bec4,0xbf80bf4abf7dbf2c,0x3dfb3f393e953f55,0xbe603ee6bd493f18,0x3f7f3f513f7f3f35,0x3f6a3f773f783f67,
0x3f0e3f7b3f353f80,0x3e483f553ec43f6d,0xbf55be48bf350000,0xbf7bbf0ebf6dbec4,0xbf0ebf7bbf35bf80,0xbe48bf55bec4bf6d,0x3f553e483f350000,0x3f7b3f0e3f6d3ec4,
0xbf55be48bf358000,0xbf7bbf0ebf6dbec4,0xbf0ebf7bbf35bf80,0xbe48bf55bec4bf6d,0x3f553e483f358000,0x3f7b3f0e3f6d3ec4,0x3f0e3f7b3f353f80,0x3e483f553ec43f6d,
0x3efcbeb83e95bf0e,0x3f513d973f2cbe16,0xbf73bf58bf7fbf35,0xbf39bf7ebf5cbf71,0xbf4abcc9bf223e48,0xbf7abee6bf67be79,0x3f423f7c3f623f6d,0x3ecf3f773f183f80,
0x3f5f3f6f3f753f55,0x3f133f7f3f3e3f7d,0x3ea1bf093dc9bf35,0x3f31bdfb3f04beac,0xbf1dbf80bf46bf7b,0xbe60bf65bedbbf78,0xbf273e2fbef13ec4,0xbf6abe89bf4ebd49,
0xbf67bf5cbf7bbf35,0xbf18bf80bf46bf75,0x3f3ebe163f0ebec4,0x3f783eac3f623dc9,0x3f713e793f550000,0x3f7d3f2c3f7f3ef1,0xbd493f4e3e483f6d,0xbf043edbbe953f22,
0x3edbbf043e48bf35,0x3f4ebd493f22be95,0x3f2c3f7d3f553f6d,0x3e793f713ef13f7f,0x3eac3f783f0e3f80,0xbe163f3e3dc93f62,0xbf80bf18bf7bbec4,0xbf5cbf67bf75bf46,
0xbf313ea1bef13f0e,0xbf77be60bf5c3d49,0x3f7c3f1d3f7f3ec4,0x3f423f6f3f673f4e,0xbecfbf7fbf22bf7b,0x3dfbbf51be16bf71,0xbf093efcbe953f35,0xbf65bcc9bf3e3e79,
0xbf39bf73bf62bf55,0xbe89bf7abf04bf80,0xbe2f3f4a3dc93f6d,0xbf273eb8bedb3f18,0x3f6a3d973f46be48,0x3f7e3f133f7d3eac,0xbf58bf5fbf75bf35,0xbee6bf80bf2cbf78,
0xbdc9bf75bec4bf80,0x3ef1bf223e48bf55,0x3f463f623f6d3f35,0x3e953f7f3f0e3f7b,0xbf7fbe95bf6d0000,0xbf62bf46bf7bbf0e,0x3f22bef13ec4bf35,0x3f753dc93f55be48,
0x3f7f3e953f6d8000,0x3f623f463f7b3f0e,0xbf223ef1bec43f35,0xbf75bdc9bf553e48,0xbdc9bf75bec4bf80,0x3ef1bf223e48bf55,0x3f463f623f6d3f35,0x3e953f7f3f0e3f7b,
0xbf7abefcbf7fbe48,0xbf27bf6abf5cbf3e,0x3f313f653f623f35,0x3dfb3f7c3edb3f7d,0xbf133f1dbe953f55,0xbf733cc9bf4e3eac,0x3f6fbd973f46bec4,0x3f773f093f803e79,
0x3e60bf5fbdc9bf7b,0x3f42becf3f04bf2c,0xbf393ee6bef13f35,0xbf7ebe2fbf673e16,0xbf51bf4abf75bf0e,0xbea1bf80bf18bf71,0x3eb83f7f3f223f6d,0xbe893f583d493f78,
0xbf4e3edbbf0e3f35,0xbf80be79bf753dc9,0x3f04bf3e3e48bf6d,0x3f71be163f46bef1,0xbf7dbeacbf7b0000,0xbf2cbf5cbf62bf22,0x3f78bd493f55bec4,0x3f673f183f7f3e95,
0xbf18bf67bf55bf35,0x3d49bf78be95bf7f,0x3f5c3f2c3f7b3ec4,0x3eac3f7d3f223f62,0x3e16bf71be48bf80,0x3f3ebf043ef1bf46,0x3e793f803f0e3f6d,0xbedb3f4ebdc93f75,
0xbee63f58bdc93f7b,0xbf6f3e89bf3e3f18,0x3f1dbf393e95bf6d,0x3f7cbd973f5cbedb,0xbf423f13bef13f55,0xbf80bdfbbf713e79,0x3f5fbecf3f22bf35,0x3f7a3ea13f7dbd49,
0xbf65bf09bf7fbe48,0xbeb8bf77bf2cbf4e,0x3f4a3f313f753ec4,0x3e2f3f7f3f043f67,0xbf27bf51bf62bf0e,0x3cc9bf7ebeacbf78,0x3efc3f6a3f463f35,0xbe603f733e163f80,
0xbec43f6d00003f80,0xbf6d3ec4bf353f35,0x3ec4bf6d0000bf80,0x3f6dbec43f35bf35,0xbec43f6d00003f80,0xbf6d3ec4bf353f35,0x3ec4bf6d0000bf80,0x3f6dbec43f35bf35,
0xbf6dbec4bf808000,0xbec4bf6dbf35bf35,0x3f6d3ec43f808000,0x3ec43f6d3f353f35,0xbf6dbec4bf808000,0xbec4bf6dbf35bf35,0x3f6d3ec43f808000,0x3ec43f6d3f353f35,
0x3d973f7c3ef13f55,0xbf313f4abeac3f78,0xbe89bf6fbf22bf35,0x3f09bf653e16bf80,0xbea13f7a3dc93f7b,0xbf6a3efcbf2c3f4e,0x3dfbbf80be95bf6d,0x3f51bf273f04bf67,
0xbf7f3e2fbf623f0e,0xbf39bf1dbf71be79,0x3f77beb83f46bf35,0x3f583ee63f7d3d49,0xbf73be60bf7f3e48,0xbecfbf5fbf3ebf18,0x3f7e3cc93f75bec4,0x3f133f423f5c3edb,
0x3e163f713f0e3f35,0xbf2c3f5cbe953f7f,0x3e79bf80be48bf6d,0x3f67bf183f22bf62,0x3f4e3edb3f7b0000,0x3d493f783ef13f46,0xbf04bf3ebf55bec4,0x3eacbf7dbdc9bf75,
0xbf7d3eacbf553f35,0xbf3ebf04bf75bdc9,0x3f783d493f7bbec4,0x3edb3f4e3f463ef1,0xbf183f67be483f80,0xbf803e79bf623f22,0x3f5cbf2c3f0ebf6d,0x3f713e163f7fbe95,
0xbe2f3f7e3e953f55,0xbf653f31bf183f71,0xbecfbf42bf46bec4,0x3efcbf7a3d49bf78,0x3f583e893f7fbe48,0x3d973f6f3f043f2c,0xbf803ea1bf623f35,0xbf1dbf13bf67be16,
0xbf7c3dfbbf753f0e,0xbee6bf39bf4ebeac,0x3f6abf273f22bf6d,0x3f5f3e603f80be79,0xbf093f77bdc93f7b,0xbf7f3eb8bf5c3f3e,0xbcc9bf73bef1bf35,0x3f4abf513edbbf7d,
0x3f46bf623ec4bf80,0x3f75bdc93f7bbf0e,0xbf7f3e95bf6d3f35,0xbef1bf22bf55be48,0x3f223ef13f6d0000,0xbe953f7f3e483f55,0x3dc9bf75bec4bf35,0x3f62bf463f0ebf7b,
0x3f223ef13f6d8000,0xbe953f7f3e483f55,0x3dc9bf75bec4bf35,0x3f62bf463f0ebf7b,0xbf463f62bec43f80,0xbf753dc9bf7b3f0e,0x3f7fbe953f6dbf35,0x3ef13f223f553e48,
0x3f6fbf423f22bf7b,0x3f4a3e2f3f7dbeac,0xbe603f773e953f35,0xbf733f39bf2c3f78,0xbcc93f653ef13f0e,0xbf5f3f58bf043f80,0xbf51bdfbbf7f3ec4,0x3d97bf6abedbbf18,
0x3eb83f273f463e48,0xbf1d3f7cbe163f71,0xbf7a3e89bf753f35,0xbea1bf31bf3ebe79,0xbf803ee6bf623f55,0xbefcbf09bf5cbd49,0x3f13bf7e3dc9bf6d,0x3f7fbecf3f67bf4e,
0x3f71be793f7bbf35,0x3e163f3e3f223e95,0xbd49bf4ebf0ebec4,0x3f5cbf673ef1bf7f,0xbedbbf04bf550000,0x3f18bf803dc9bf62,0xbf2c3f7dbe483f6d,0xbf783eacbf753f46,
0xbeac3f783e483f35,0xbf7d3f2cbf463f75,0x3f80bf183f55bf6d,0x3f043edb3f62bdc9,0x3f67bf5c3f0ebf80,0x3f4e3d493f7fbef1,0xbf3ebe16bf7b3ec4,0x3e79bf71be95bf22,
0x3dfb3f313f223e48,0xbf583f73bedb3f78,0xbf7f3f13bf623f6d,0xbeb8befcbf4e3d49,0x3e89bf6abe95bf0e,0x3f7cbf423f3ebf7d,0x3f65be603f7fbf35,0xbcc93f4a3f043eac,
0xbf7e3f39bf463f7b,0xbf09bea1bf673e79,0x3d97bf51bef1bec4,0x3f6fbf5f3f18bf80,0x3f77becf3f75bf55,0x3e2f3f273f2c3e16,0xbee63f7a3dc93f35,0xbf803f1dbf5c3f71,
0xbf7b3f55bf353f80,0xbf0ebe48bf6d3ec4,0x3e483f0e3f350000,0xbf553f7bbec43f6d,0x3f7bbf553f35bf80,0x3f0e3e483f6dbec4,0xbe48bf0ebf350000,0x3f55bf7b3ec4bf6d,
0xbe48bf0ebf358000,0x3f55bf7b3ec4bf6d,0xbf7b3f55bf353f80,0xbf0ebe48bf6d3ec4,0x3e483f0e3f358000,0xbf553f7bbec43f6d,0x3f7bbf553f35bf80,0x3f0e3e483f6dbec4,
0xbf1dbcc9bf753f0e,0x3f09bf73bd49bf18,0x3f27bf7c3dc9bf35,0x3f6fbefc3f78bf67,0x3e893ecf3f46be48,0xbf513f7fbeac3f5c,0xbf653f7abef13f6d,0xbf393dfbbf7d3f2c,
0x3f4abf803e95bf55,0x3f58bea13f80bf4e,0x3f42be2f3f7fbf35,0xbeb83f5f3e793edb,0xbf773f6abf223f7b,0xbf13bd97bf713f04,0xbee6be60bf623ec4,0x3f31bf7e3e16bf3e,
0x3f3ebf7d3e48bf35,0x3f5cbedb3f7fbf62,0xbeacbe79bf553ec4,0x3f4ebf803e95bf46,0xbd493f183f0e0000,0xbf783f71bf223f75,0x3f67bf043f7bbf6d,0xbe163f2c3ef13dc9,
0x3f2cbe163f7bbf35,0xbf043f673dc93ef1,0x3f71bf783f0ebf6d,0x3f18bd493f75bf22,0xbf803f4ebf553f80,0xbe79beacbf463e95,0xbedb3f5c3e483ec4,0xbf7d3f3ebf623f7f,
0x3ecf3d973f62bf0e,0xbf4a3f7cbe793f2c,0xbf093f5f3dc93ec4,0xbf733f31bf713f7d,0xbf803f65bf463f7b,0xbe89be60bf4e3edb,0xbf133dfbbf753f35,0x3f27bf6f3d49bf04,
0xbf6a3f7fbef13f55,0xbf1d3e2fbf783f3e,0xbf583efcbf7f3f6d,0x3ea1bf39beacbe16,0xbcc9bee6bf223e48,0x3f77bf7a3f18bf67,0x3f51bf7e3e95bf35,0x3f42beb83f80bf5c,
0x3f75bf463f6dbf80,0xbdc93ef13f0ebe48,0x3f62bf7f3ec4bf35,0x3f22be953f7bbf55,0x3e95bf22bec40000,0x3f7fbf623f55bf7b,0xbef13dc9bf6d3f35,0x3f46bf753e48bf0e,
0xbe953f223ec48000,0xbf7f3f62bf553f7b,0x3ef1bdc93f6dbf35,0xbf463f75be483f0e,0x3f75bf463f6dbf80,0xbdc93ef13f0ebe48,0x3f62bf7f3ec4bf35,0x3f22be953f7bbf55,
0xbf133f4a3dc93e48,0xbf653f39bf783f80,0xbf6f3f7fbef13f35,0xbefc3e60bf713f4e,0x3f09be893f75bf55,0xbf423f6abe163edb,0xbcc93ea13f22bec4,0xbf7e3f7cbf2c3f5c,
0xbf513f1dbf7f3f7b,0x3ee6bf31be79bd49,0xbeb83d97bf623f35,0x3f5fbf7a3eacbf18,0xbf583f77be953f0e,0xbf273ecfbf7d3f67,0xbf803f73bf463f6d,0xbdfbbe2fbf3e3f04,
0xbe793d49bf553f35,0x3f71bf7d3ef1bf22,0xbf183edbbf7b3f6d,0x3f3ebf5c3dc9be95,0x3f04bf2cbe480000,0x3f67bf4e3f75bf7f,0x3e16beacbf0e3ec4,0x3f80bf783f46bf62,
0x3f78bf803f0ebf35,0x3eacbe163f62bf46,0x3f4ebf673e48bec4,0x3f2cbf043f7fbf75,0x3f5cbf3e3f7bbf80,0xbedb3f183e95bdc9,0x3f7dbf713f55bf6d,0xbd493e793f22bef1,
0x3f27bf133f7fbf7b,0xbf393f4abd493e16,0x3efcbecf3f75bf6d,0xbf583f65be793eac,0x3ea1be603f62bf55,0xbf6f3f77bedb3f04,0x3dfbbcc93f46bf35,0xbf7c3f7fbf183f2c,
0xbf423f51bdc93e48,0xbf313f1dbf803f7d,0xbf5f3f6abe953ec4,0xbf093ee6bf783f71,0xbf733f7abef13f0e,0xbeb83e89bf673f5c,0xbf7e3f80bf223f35,0xbe2f3d97bf4e3f3e,
0x3f003f003f003f00,0x3f003f003f003f00,0x3f003f003f003f00,0x3f003f003f003f00,0x3f003f003f003f00,0x3f003f003f003f00,0x3f003f003f003f00,0x3f003f003f003f00,
0xbf00bf003f003f00,0xbf00bf003f003f00,0xbf00bf003f003f00,0xbf00bf003f003f00,0xbf00bf003f003f00,0xbf00bf003f003f00,0xbf00bf003f003f00,0xbf00bf003f003f00,
0xbf73bf7abf75bf7b,0xbf6fbf77bf71bf78,0xbf7ebf80bf7fbf80,0xbf7cbf7fbf7dbf80,0xbf42bf51bf46bf55,0xbf39bf4abf3ebf4e,0xbf5fbf6abf62bf6d,0xbf58bf65bf5cbf67,
0x3ea13e603e953e48,0x3eb83e893eac3e79,0x3dfb3cc93dc98000,0x3e2f3d973e163d49,0x3f273f133f223f0e,0x3f313f1d3f2c3f18,0x3efc3ecf3ef13ec4,0x3f093ee63f043edb,
0x3f043f2c3f0e3f35,0x3edb3f183ef13f22,0x3e163eac3e483ec4,0x3d493e793dc93e95,0x3f783f803f7b3f80,0x3f713f7d3f753f7f,0x3f4e3f673f553f6d,0x3f3e3f5c3f463f62,
0xbf5cbf3ebf55bf35,0xbf67bf4ebf62bf46,0xbf7dbf71bf7bbf6d,0xbf80bf78bf7fbf75,0xbe79bd49be488000,0xbeacbe16be95bdc9,0xbf18bedbbf0ebec4,0xbf2cbf04bf22bef1,
0x3f093e893ef13e48,0x3f273ecf3f183eac,0xbcc9bea1bdc9bec4,0x3dfbbe2f3d49be79,0xbf13bf4abf22bf55,0xbee6bf31bf04bf3e,0xbf6fbf7fbf75bf80,0xbf5fbf7abf67bf7d,
0x3f583f773f623f7b,0x3f423f6a3f4e3f71,0x3f803f733f7f3f6d,0x3f7e3f7c3f803f78,0x3f513f1d3f463f0e,0x3f653f393f5c3f2c,0x3eb83d973e958000,0x3efc3e603edb3e16,
0x3f623f7f3f6d3f80,0x3f463f753f553f7b,0x3e953f223ec43f35,0x3dc93ef13e483f0e,0xbef1bdc9bec40000,0xbf22be95bf0ebe48,0xbf75bf46bf6dbf35,0xbf7fbf62bf7bbf55,
0xbef1bdc9bec48000,0xbf22be95bf0ebe48,0xbf75bf46bf6dbf35,0xbf7fbf62bf7bbf55,0xbf62bf7fbf6dbf80,0xbf46bf75bf55bf7b,0xbe95bf22bec4bf35,0xbdc9bef1be48bf0e,
0x3cc9bee6bdc9bf0e,0x3e89be603e16beac,0xbf51bf7ebf62bf80,0xbf27bf6fbf3ebf78,0x3f6a3f7f3f753f7b,0x3f4a3f7c3f5c3f80,0x3f583efc3f463ec4,0x3f733f313f673f18,
0x3f803f653f7f3f55,0x3f773f7a3f7d3f71,0x3f133dfb3ef18000,0x3f423eb83f2c3e79,0xbecf3d97be953e48,0xbf1dbe2fbf04bd49,0x3f093f5f3f223f6d,0x3ea13f393edb3f4e,
0xbf80bf4ebf7bbf35,0xbf78bf71bf7fbf62,0xbedbbf5cbf0ebf6d,0xbe16bf2cbe95bf46,0x3f3e3f7d3f553f80,0x3f043f673f223f75,0xbeac3e79be483ec4,0xbf18bd49bef13dc9,
0xbd49bf18be48bf35,0x3e79beac3dc9bef1,0x3f673f043f553ec4,0x3f7d3f3e3f753f22,0xbf2cbe16bf0e8000,0xbf5cbedbbf46be95,0xbf71bf78bf7bbf6d,0xbf4ebf80bf62bf7f,
0xbe893ecfbdc93f0e,0xbf133d97bedb3e79,0x3f653f7a3f753f6d,0x3f313f7e3f4e3f80,0x3f1dbcc93ef1be48,0x3f583ea13f3e3e16,0xbf27bf7cbf46bf80,0xbeb8bf5fbf04bf71,
0xbf77bf6abf7fbf55,0xbf51bf7fbf67bf78,0xbee63e60be953ec4,0xbf39bdfbbf183d49,0x3f4a3f803f623f7b,0x3f093f733f2c3f7d,0x3f423e2f3f228000,0x3f6f3efc3f5c3eac,
0x3f0e3f7b3f353f80,0x3e483f553ec43f6d,0xbf55be48bf350000,0xbf7bbf0ebf6dbec4,0xbf0ebf7bbf35bf80,0xbe48bf55bec4bf6d,0x3f553e483f350000,0x3f7b3f0e3f6d3ec4,
0xbf55be48bf358000,0xbf7bbf0ebf6dbec4,0xbf0ebf7bbf35bf80,0xbe48bf55bec4bf6d,0x3f553e483f358000,0x3f7b3f0e3f6d3ec4,0x3f0e3f7b3f353f80,0x3e483f553ec43f6d,
0x3f773ecf3f623e48,0x3f7c3f423f803f18,0xbee6bf7abf22bf80,0xbcc9bf4abe79bf67,0xbf7ebf39bf7fbf0e,0xbf58bf73bf71bf5c,0x3d973f513e953f6d,0xbeb83efcbe163f2c,
0x3e893f6a3ef13f7b,0xbe2f3f273d493f4e,0x3f653e603f468000,0x3f803f1d3f783edb,0x3dfbbf31bdc9bf55,0x3f09bea13eacbf04,0xbf7fbf13bf75bec4,0xbf6fbf5fbf7dbf3e,
0x3edbbf043e48bf35,0x3f4ebd493f22be95,0x3f2c3f7d3f553f6d,0x3e793f713ef13f7f,0x3eac3f783f0e3f80,0xbe163f3e3dc93f62,0xbf80bf18bf7bbec4,0xbf5cbf67bf75bf46,
0x3f673f5c3f7b3f35,0x3f183f803f463f75,0xbf3e3e16bf0e3ec4,0xbf78beacbf62bdc9,0xbf71be79bf558000,0xbf7dbf2cbf7fbef1,0x3d49bf4ebe48bf6d,0x3f04bedb3e95bf22,
0xbcc9bf65be95bf7b,0x3efcbf093e79bf3e,0xbf513dfbbf223ec4,0xbf7fbecfbf71be16,0x3f6f3f423f7f3f0e,0x3f1d3f7c3f4e3f67,0xbe60bf77bef1bf80,0x3ea1bf313d49bf5c,
0x3f803ee63f753e48,0x3f5f3f583f783f2c,0xbf13bf7ebf46bf6d,0xbd97bf6abeacbf7d,0xbeb83f27bdc93f55,0xbf4a3e2fbf183edb,0x3f7a3e893f628000,0x3f733f393f803f04,
0x3dc93f753ec43f80,0xbef13f22be483f55,0xbf46bf62bf6dbf35,0xbe95bf7fbf0ebf7b,0x3f7f3e953f6d0000,0x3f623f463f7b3f0e,0xbf223ef1bec43f35,0xbf75bdc9bf553e48,
0xbf7fbe95bf6d8000,0xbf62bf46bf7bbf0e,0x3f22bef13ec4bf35,0x3f753dc93f55be48,0x3dc93f753ec43f80,0xbef13f22be483f55,0xbf46bf62bf6dbf35,0xbe95bf7fbf0ebf7b,
0x3f093f773f463f55,0xbd973f6f3e793f80,0x3cc9bf73be95bf80,0x3f1dbf133eacbf4e,0x3f7c3dfb3f62be48,0x3f653f313f7d3edb,0xbf6abf27bf7fbec4,0xbefcbf7abf3ebf5c,
0xbf583e89bf223f0e,0xbf7fbeb8bf78bd49,0x3f803ea13f758000,0x3f4a3f513f713f18,0x3e2f3f7e3ef13f7b,0xbee63f39be163f67,0x3ecfbf423dc9bf6d,0x3f5fbe603f2cbf04,
0x3f183f673f553f35,0xbd493f783e953f7f,0xbf5cbf2cbf7bbec4,0xbeacbf7dbf22bf62,0xbe163f713e483f80,0xbf3e3f04bef13f46,0xbe79bf80bf0ebf6d,0x3edbbf4e3dc9bf75,
0xbf4e3edbbf0e3f35,0xbf80be79bf753dc9,0x3f04bf3e3e48bf6d,0x3f71be163f46bef1,0xbf7dbeacbf7b8000,0xbf2cbf5cbf62bf22,0x3f78bd493f55bec4,0x3f673f183f7f3e95,
0x3ea13f7a3f223f55,0xbecf3f5fbd493f7d,0xbdfbbf80bef1bf6d,0x3f13bf423e79bf71,0xbd973f7c3e953f7b,0xbf393f1dbedb3f5c,0x3e89bf6fbdc9bf80,0x3f58bee63f18bf3e,
0xbf733e60bf463f0e,0xbf6abefcbf80be16,0x3f7ebcc93f62bec4,0x3f513f273f783eac,0xbf7fbe2fbf753e48,0xbf31bf4abf67bf04,0x3f773eb83f7f8000,0x3f093f653f4e3f2c,
0xbec43f6d00003f80,0xbf6d3ec4bf353f35,0x3ec4bf6d0000bf80,0x3f6dbec43f35bf35,0xbec43f6d00003f80,0xbf6d3ec4bf353f35,0x3ec4bf6d0000bf80,0x3f6dbec43f35bf35,
0xbf6dbec4bf808000,0xbec4bf6dbf35bf35,0x3f6d3ec43f808000,0x3ec43f6d3f353f35,0xbf6dbec4bf808000,0xbec4bf6dbf35bf35,0x3f6d3ec43f808000,0x3ec43f6d3f353f35,
0xbf273f51be953f7b,0xbf803dfbbf673f04,0x3efcbf6a3dc9bf80,0x3f7abea13f4ebf2c,0xbf653f09bf223f55,0xbf6fbe89bf803e16,0x3f4abf313ef1bf6d,0x3f7c3d973f78beac,
0xbf42bf13bf75be48,0xbcc9bf7ebedbbf5c,0x3f5f3ecf3f7f8000,0x3e603f733f183f3e,0xbee6bf58bf46bf0e,0x3eb8bf77bd49bf7d,0x3f1d3f393f623ec4,0xbe2f3f7f3e793f71,
0xbf7d3eacbf553f35,0xbf3ebf04bf75bdc9,0x3f783d493f7bbec4,0x3edb3f4e3f463ef1,0xbf183f67be483f80,0xbf803e79bf623f22,0x3f5cbf2c3f0ebf6d,0x3f713e163f7fbe95,
0xbe16bf71bf0ebf35,0x3f2cbf5c3e95bf7f,0xbe793f803e483f6d,0xbf673f18bf223f62,0xbf4ebedbbf7b8000,0xbd49bf78bef1bf46,0x3f043f3e3f553ec4,0xbeac3f7d3dc93f75,
0xbf13bf1dbf62be48,0x3ea1bf80be16bf67,0x3f6f3d973f7fbec4,0x3e893f583f2c3f04,0xbf7a3efcbf463f55,0xbf42becfbf783d49,0x3f31bf653e95bf80,0x3f7ebe2f3f71bf18,
0x3f51bf4a3ef1bf7b,0x3f733cc93f7dbedb,0xbeb83f7f3dc93f6d,0xbf773f09bf3e3f5c,0xbe60bf5fbf22bf0e,0x3f27bf6a3e79bf80,0x3f393ee63f758000,0xbdfb3f7c3eac3f4e,
0xbf463f62bec43f80,0xbf753dc9bf7b3f0e,0x3f7fbe953f6dbf35,0x3ef13f223f553e48,0xbf22bef1bf6d0000,0x3e95bf7fbe48bf55,0xbdc93f753ec43f35,0xbf623f46bf0e3f7b,
0xbf22bef1bf6d8000,0x3e95bf7fbe48bf55,0xbdc93f753ec43f35,0xbf623f46bf0e3f7b,0x3f46bf623ec4bf80,0x3f75bdc93f7bbf0e,0xbf7f3e95bf6d3f35,0xbef1bf22bf55be48,
0xbf6a3d97bf7f3f0e,0xbdfbbf51bf18bedb,0x3f58bf5f3ef1bf80,0x3f65bcc93f80bf04,0x3f39bf733e95bf7b,0x3f77be603f78bf2c,0x3e2f3f4a3f223ec4,0xbf423f6fbeac3f7d,
0x3ecfbf7fbdc9bf55,0x3f7ebf133f4ebf67,0x3f093efc3f628000,0xbee63f803d493f5c,0x3f313ea13f75be48,0xbe893f7a3e793f3e,0xbf7c3f1dbf463f6d,0xbf27beb8bf713e16,
0x3eacbf78be48bf35,0x3f7dbf2c3f46bf75,0xbf803f18bf553f6d,0xbf04bedbbf623dc9,0xbf673f5cbf0e3f80,0xbf4ebd49bf7f3ef1,0x3f3e3e163f7bbec4,0xbe793f713e953f22,
0x3f71be793f7bbf35,0x3e163f3e3f223e95,0xbd49bf4ebf0ebec4,0x3f5cbf673ef1bf7f,0xbedbbf04bf558000,0x3f18bf803dc9bf62,0xbf2c3f7dbe483f6d,0xbf783eacbf753f46,
0x3f4abcc93f7fbf0e,0xbe603f653eac3f04,0xbf423f7cbe953f6d,0xbf6a3e89bf7d3f3e,0xbefcbeb8bf623e48,0x3f13bf7f3d49bf4e,0x3f73bf583f22bf80,0x3f313dfb3f78bedb,
0xbf1d3f80bdc93f55,0xbf7a3ee6bf713f5c,0xbf27be2fbf753ec4,0x3ecfbf77be16bf2c,0x3f5fbf6f3ef1bf7b,0x3f51bd973f80bf18,0x3ea13f093f468000,0xbf393f7ebe793f67,
0xbf7b3f55bf353f80,0xbf0ebe48bf6d3ec4,0x3e483f0e3f350000,0xbf553f7bbec43f6d,0x3f7bbf553f35bf80,0x3f0e3e483f6dbec4,0xbe48bf0ebf350000,0x3f55bf7b3ec4bf6d,
0xbe48bf0ebf358000,0x3f55bf7b3ec4bf6d,0xbf7b3f55bf353f80,0xbf0ebe48bf6d3ec4,0x3e483f0e3f358000,0xbf553f7bbec43f6d,0x3f7bbf553f35bf80,0x3f0e3e483f6dbec4,
0x3dfbbf39bef1be48,0x3f7abf653f2cbf7d,0x3f7fbf513f46bf80,0x3ecf3e893f5cbeac,0xbefc3f6f3dc93f0e,0xbf7c3f27bf673f78,0xbf733f09bf753f6d,0xbcc9bf1dbf18bd49,
0x3f7ebf313f62bf7b,0x3e603ee63f3ebe16,0x3d973f133f228000,0xbf6a3f77bf043f71,0xbf5f3eb8bf7f3f55,0x3e2fbf42bedbbe79,0x3ea1bf58be95bec4,0x3f80bf4a3f4ebf80,
0x3f2cbe163f7bbf35,0xbf043f673dc93ef1,0x3f71bf783f0ebf6d,0x3f18bd493f75bf22,0xbf803f4ebf553f80,0xbe79beacbf463e95,0xbedb3f5c3e483ec4,0xbf7d3f3ebf623f7f,
0xbf3e3f7dbe483f35,0xbf5c3edbbf7f3f62,0x3eac3e793f55bec4,0xbf4e3f80be953f46,0x3d49bf18bf0e8000,0x3f78bf713f22bf75,0xbf673f04bf7b3f6d,0x3e16bf2cbef1bdc9,
0xbf6f3f27bf753f7b,0x3dfbbf13bf043d49,0xbe60be89bf463ec4,0x3f65bf803edbbf4e,0x3f31bf733dc9bf0e,0x3f5fbf093f7dbf71,0x3f7cbf4a3f62bf80,0x3d973ecf3f2cbe79,
0x3eb8bf42be95be48,0x3f7ebf513f5cbf80,0x3f7abf773f22bf6d,0x3ee63cc93f67bf18,0x3f39bea13f7fbf55,0xbefc3f583e163eac,0xbe2f3f1d3ef18000,0xbf7f3f6abf3e3f78,
0xbf753f46bf6d3f80,0x3dc9bef1bf0e3e48,0xbf623f7fbec43f35,0xbf223e95bf7b3f55,0xbe953f223ec40000,0xbf7f3f62bf553f7b,0x3ef1bdc93f6dbf35,0xbf463f75be483f0e,
0x3e95bf22bec48000,0x3f7fbf623f55bf7b,0xbef13dc9bf6d3f35,0x3f46bf753e48bf0e,0xbf753f46bf6d3f80,0x3dc9bef1bf0e3e48,0xbf623f7fbec43f35,0xbf223e95bf7b3f55,
0x3f7cbf7e3f22bf55,0x3ea1bcc93f5cbf2c,0x3f6abf423f75bf80,0xbe893f093edbbe16,0x3e60befcbef13e48,0x3f7fbf6f3f4ebf71,0x3f39bf653dc9bec4,0x3f4abf133f80bf78,
0x3e2f3dfb3f46bf0e,0xbf733f80bf043f3e,0xbecf3f273e958000,0xbf773f58bf673f7d,0x3f7abf5f3f62bf7b,0xbd973eb83f18beac,0x3f31bee63f7fbf6d,0xbf1d3f513d493e79,
0xbf783f80bf0e3f35,0xbeac3e16bf623f46,0xbf4e3f67be483ec4,0xbf2c3f04bf7f3f75,0xbf5c3f3ebf7b3f80,0x3edbbf18be953dc9,0xbf7d3f71bf553f6d,0x3d49be79bf223ef1,
0xbe793d49bf553f35,0x3f71bf7d3ef1bf22,0xbf183edbbf7b3f6d,0x3f3ebf5c3dc9be95,0x3f04bf2cbe488000,0x3f67bf4e3f75bf7f,0x3e16beacbf0e3ec4,0x3f80bf783f46bf62,
0x3f7fbf7c3f46bf55,0xbcc93dfb3f2cbf18,0x3f77bf6f3f62bf6d,0xbe603ea13f04bedb,0x3f65bf583f75bf7b,0xbecf3efc3eacbe79,0x3f4abf393f7fbf80,0xbf133f273e16bd49,
0xbd973e2f3f22bf0e,0xbf803f7ebf3e3f4e,0xbe893eb83ef1bec4,0xbf7a3f73bf5c3f67,0xbee63f093e95be48,0xbf6a3f5fbf713f78,0xbf1d3f313dc98000,0xbf513f42bf7d3f80,
0x3f003f003f003f00,0x3f003f003f003f00,0x3f003f003f003f00,0x3f003f003f003f00,0x3f003f003f003f00,0x3f003f003f003f00,0x3f003f003f003f00,0x3f003f003f003f00,
0xbf00bf003f003f00,0xbf00bf003f003f00,0xbf00bf003f003f00,0xbf00bf003f003f00,0xbf00bf003f003f00,0xbf00bf003f003f00,0xbf00bf003f003f00,0xbf00bf003f003f00,
0xbee6bf09bef1bf0e,0xbecfbefcbedbbf04,0xbf1dbf31bf22bf35,0xbf13bf27bf18bf2c,0xbd97be2fbdc9be48,0xbcc9bdfbbd49be16,0xbe89beb8be95bec4,0xbe60bea1be79beac,
0x3f653f583f623f55,0x3f6a3f5f3f673f5c,0x3f4a3f393f463f35,0x3f513f423f4e3f3e,0x3f7f3f7c3f7f3f7b,0x3f803f7e3f803f7d,0x3f773f6f3f753f6d,0x3f7a3f733f783f71,
0xbf5cbf3ebf55bf35,0xbf67bf4ebf62bf46,0xbf7dbf71bf7bbf6d,0xbf80bf78bf7fbf75,0xbe79bd49be480000,0xbeacbe16be95bdc9,0xbf18bedbbf0ebec4,0xbf2cbf04bf22bef1,
0xbf04bf2cbf0ebf35,0xbedbbf18bef1bf22,0xbe16beacbe48bec4,0xbd49be79bdc9be95,0xbf78bf80bf7bbf80,0xbf71bf7dbf75bf7f,0xbf4ebf67bf55bf6d,0xbf3ebf5cbf46bf62,
0x3e603efc3e953f0e,0x3d973eb83e163edb,0x3f393f653f463f6d,0x3f1d3f513f2c3f5c,0x3f7c3f7e3f7f3f7b,0x3f733f803f783f80,0x3f6a3f423f623f35,0x3f773f583f713f4e,
0xbf7abf5fbf75bf55,0xbf7fbf6fbf7dbf67,0xbf31bee6bf22bec4,0xbf4abf13bf3ebf04,0xbe2f3dfbbdc93e48,0xbea1bcc9be793d49,0x3ecf3f273ef13f35,0x3e893f093eac3f18,
0xbf62bf7fbf6dbf80,0xbf46bf75bf55bf7b,0xbe95bf22bec4bf35,0xbdc9bef1be48bf0e,0x3ef13dc93ec40000,0x3f223e953f0e3e48,0x3f753f463f6d3f35,0x3f7f3f623f7b3f55,
0x3ef13dc93ec48000,0x3f223e953f0e3e48,0x3f753f463f6d3f35,0x3f7f3f623f7b3f55,0x3f623f7f3f6d3f80,0x3f463f753f553f7b,0x3e953f223ec43f35,0x3dc93ef13e483f0e,
0xbf39bea1bf22be48,0xbf5fbf09bf4ebedb,0x3e2f3f1d3e953f35,0xbd973ecf3d493f04,0xbeb8bf42bef1bf55,0xbdfbbf13be79bf2c,0xbf7abf77bf7fbf6d,0xbf65bf80bf71bf7d,
0xbf31bf73bf46bf7b,0xbefcbf58bf18bf67,0xbf7cbf4abf75bf35,0xbf7fbf6abf80bf5c,0x3f6f3f273f623f0e,0x3f7e3f513f783f3e,0x3e60be893dc9bec4,0x3ee6bcc93eacbe16,
0x3d493f183e483f35,0xbe793eacbdc93ef1,0xbf67bf04bf55bec4,0xbf7dbf3ebf75bf22,0x3f2c3e163f0e0000,0x3f5c3edb3f463e95,0x3f713f783f7b3f6d,0x3f4e3f803f623f7f,
0xbf80bf4ebf7bbf35,0xbf78bf71bf7fbf62,0xbedbbf5cbf0ebf6d,0xbe16bf2cbe95bf46,0x3f3e3f7d3f553f80,0x3f043f673f223f75,0xbeac3e79be483ec4,0xbf18bd49bef13dc9,
0x3efc3f6f3f223f7b,0x3e2f3f423eac3f5c,0x3f733f093f623ec4,0x3f803f4a3f7d3f2c,0xbdfbbf39be95bf55,0x3e60bee63d49bf18,0xbf7fbf51bf7fbf35,0xbf6abf77bf78bf67,
0xbf5fbeb8bf46be48,0xbf7cbf27bf71bf04,0x3ea13f583ef13f6d,0xbcc93f1d3e163f3e,0x3f7e3f313f753f0e,0x3f7a3f653f803f4e,0x3d97bf13bdc9bf35,0x3ecfbe893e79bedb,
0x3f0e3f7b3f353f80,0x3e483f553ec43f6d,0xbf55be48bf350000,0xbf7bbf0ebf6dbec4,0xbf0ebf7bbf35bf80,0xbe48bf55bec4bf6d,0x3f553e483f350000,0x3f7b3f0e3f6d3ec4,
0xbf55be48bf358000,0xbf7bbf0ebf6dbec4,0xbf0ebf7bbf35bf80,0xbe48bf55bec4bf6d,0x3f553e483f358000,0x3f7b3f0e3f6d3ec4,0x3f0e3f7b3f353f80,0x3e483f553ec43f6d,
0x3f5f3f6f3f753f55,0x3f133f7f3f3e3f7d,0x3ea1bf093dc9bf35,0x3f31bdfb3f04beac,0xbf1dbf80bf46bf7b,0xbe60bf65bedbbf78,0xbf273e2fbef13ec4,0xbf6abe89bf4ebd49,
0xbefc3eb8be953f0e,0xbf51bd97bf2c3e16,0x3f733f583f7f3f35,0x3f393f7e3f5c3f71,0x3f4a3cc93f22be48,0x3f7a3ee63f673e79,0xbf42bf7cbf62bf6d,0xbecfbf77bf18bf80,
0x3f673f5c3f7b3f35,0x3f183f803f463f75,0xbf3e3e16bf0e3ec4,0xbf78beacbf62bdc9,0xbf71be79bf550000,0xbf7dbf2cbf7fbef1,0x3d49bf4ebe48bf6d,0x3f04bedb3e95bf22,
0xbedb3f04be483f35,0xbf4e3d49bf223e95,0xbf2cbf7dbf55bf6d,0xbe79bf71bef1bf7f,0xbeacbf78bf0ebf80,0x3e16bf3ebdc9bf62,0x3f803f183f7b3ec4,0x3f5c3f673f753f46,
0x3f393f733f623f55,0x3e893f7a3f043f80,0x3e2fbf4abdc9bf6d,0x3f27beb83edbbf18,0xbf6abd97bf463e48,0xbf7ebf13bf7dbeac,0x3f583f5f3f753f35,0x3ee63f803f2c3f78,
0xbf313ea1bef13f0e,0xbf77be60bf5c3d49,0x3f7c3f1d3f7f3ec4,0x3f423f6f3f673f4e,0xbecfbf7fbf22bf7b,0x3dfbbf51be16bf71,0xbf093efcbe953f35,0xbf65bcc9bf3e3e79,
0xbdc9bf75bec4bf80,0x3ef1bf223e48bf55,0x3f463f623f6d3f35,0x3e953f7f3f0e3f7b,0xbf7fbe95bf6d0000,0xbf62bf46bf7bbf0e,0x3f22bef13ec4bf35,0x3f753dc93f55be48,
0x3f7f3e953f6d8000,0x3f623f463f7b3f0e,0xbf223ef1bec43f35,0xbf75bdc9bf553e48,0xbdc9bf75bec4bf80,0x3ef1bf223e48bf55,0x3f463f623f6d3f35,0x3e953f7f3f0e3f7b,
0x3e60bf5fbdc9bf7b,0x3f42becf3f04bf2c,0xbf393ee6bef13f35,0xbf7ebe2fbf673e16,0xbf51bf4abf75bf0e,0xbea1bf80bf18bf71,0x3eb83f7f3f223f6d,0xbe893f583d493f78,
0x3f7a3efc3f7f3e48,0x3f273f6a3f5c3f3e,0xbf31bf65bf62bf35,0xbdfbbf7cbedbbf7d,0x3f13bf1d3e95bf55,0x3f73bcc93f4ebeac,0xbf6f3d97bf463ec4,0xbf77bf09bf80be79,
0x3f4ebedb3f0ebf35,0x3f803e793f75bdc9,0xbf043f3ebe483f6d,0xbf713e16bf463ef1,0x3f7d3eac3f7b0000,0x3f2c3f5c3f623f22,0xbf783d49bf553ec4,0xbf67bf18bf7fbe95,
0x3f183f673f553f35,0xbd493f783e953f7f,0xbf5cbf2cbf7bbec4,0xbeacbf7dbf22bf62,0xbe163f713e483f80,0xbf3e3f04bef13f46,0xbe79bf80bf0ebf6d,0x3edbbf4e3dc9bf75,
0x3f653f093f7f3e48,0x3eb83f773f2c3f4e,0xbf4abf31bf75bec4,0xbe2fbf7fbf04bf67,0x3f273f513f623f0e,0xbcc93f7e3eac3f78,0xbefcbf6abf46bf35,0x3e60bf73be16bf80,
0xbee63f58bdc93f7b,0xbf6f3e89bf3e3f18,0x3f1dbf393e95bf6d,0x3f7cbd973f5cbedb,0xbf423f13bef13f55,0xbf80bdfbbf713e79,0x3f5fbecf3f22bf35,0x3f7a3ea13f7dbd49,
0xbec43f6d00003f80,0xbf6d3ec4bf353f35,0x3ec4bf6d0000bf80,0x3f6dbec43f35bf35,0xbec43f6d00003f80,0xbf6d3ec4bf353f35,0x3ec4bf6d0000bf80,0x3f6dbec43f35bf35,
0xbf6dbec4bf808000,0xbec4bf6dbf35bf35,0x3f6d3ec43f808000,0x3ec43f6d3f353f35,0xbf6dbec4bf808000,0xbec4bf6dbf35bf35,0x3f6d3ec43f808000,0x3ec43f6d3f353f35,
0xbf7f3e2fbf623f0e,0xbf39bf1dbf71be79,0x3f77beb83f46bf35,0x3f583ee63f7d3d49,0xbf73be60bf7f3e48,0xbecfbf5fbf3ebf18,0x3f7e3cc93f75bec4,0x3f133f423f5c3edb,
0xbd97bf7cbef1bf55,0x3f31bf4a3eacbf78,0x3e893f6f3f223f35,0xbf093f65be163f80,0x3ea1bf7abdc9bf7b,0x3f6abefc3f2cbf4e,0xbdfb3f803e953f6d,0xbf513f27bf043f67,
0xbe16bf71bf0ebf35,0x3f2cbf5c3e95bf7f,0xbe793f803e483f6d,0xbf673f18bf223f62,0xbf4ebedbbf7b0000,0xbd49bf78bef1bf46,0x3f043f3e3f553ec4,0xbeac3f7d3dc93f75,
0x3f7dbeac3f55bf35,0x3f3e3f043f753dc9,0xbf78bd49bf7b3ec4,0xbedbbf4ebf46bef1,0x3f18bf673e48bf80,0x3f80be793f62bf22,0xbf5c3f2cbf0e3f6d,0xbf71be16bf7f3e95,
0x3f7cbdfb3f75bf0e,0x3ee63f393f4e3eac,0xbf6a3f27bf223f6d,0xbf5fbe60bf803e79,0x3f09bf773dc9bf7b,0x3f7fbeb83f5cbf3e,0x3cc93f733ef13f35,0xbf4a3f51bedb3f7d,
0xbe2f3f7e3e953f55,0xbf653f31bf183f71,0xbecfbf42bf46bec4,0x3efcbf7a3d49bf78,0x3f583e893f7fbe48,0x3d973f6f3f043f2c,0xbf803ea1bf623f35,0xbf1dbf13bf67be16,
0x3f46bf623ec4bf80,0x3f75bdc93f7bbf0e,0xbf7f3e95bf6d3f35,0xbef1bf22bf55be48,0x3f223ef13f6d0000,0xbe953f7f3e483f55,0x3dc9bf75bec4bf35,0x3f62bf463f0ebf7b,
0x3f223ef13f6d8000,0xbe953f7f3e483f55,0x3dc9bf75bec4bf35,0x3f62bf463f0ebf7b,0xbf463f62bec43f80,0xbf753dc9bf7b3f0e,0x3f7fbe953f6dbf35,0x3ef13f223f553e48,
0x3eb83f273f463e48,0xbf1d3f7cbe163f71,0xbf7a3e89bf753f35,0xbea1bf31bf3ebe79,0xbf803ee6bf623f55,0xbefcbf09bf5cbd49,0x3f13bf7e3dc9bf6d,0x3f7fbecf3f67bf4e,
0xbf6f3f42bf223f7b,0xbf4abe2fbf7d3eac,0x3e60bf77be95bf35,0x3f73bf393f2cbf78,0x3cc9bf65bef1bf0e,0x3f5fbf583f04bf80,0x3f513dfb3f7fbec4,0xbd973f6a3edb3f18,
0xbf713e79bf7b3f35,0xbe16bf3ebf22be95,0x3d493f4e3f0e3ec4,0xbf5c3f67bef13f7f,0x3edb3f043f550000,0xbf183f80bdc93f62,0x3f2cbf7d3e48bf6d,0x3f78beac3f75bf46,
0x3eacbf78be48bf35,0x3f7dbf2c3f46bf75,0xbf803f18bf553f6d,0xbf04bedbbf623dc9,0xbf673f5cbf0e3f80,0xbf4ebd49bf7f3ef1,0x3f3e3e163f7bbec4,0xbe793f713e953f22,
0x3f7ebf393f46bf7b,0x3f093ea13f67be79,0xbd973f513ef13ec4,0xbf6f3f5fbf183f80,0xbf773ecfbf753f55,0xbe2fbf27bf2cbe16,0x3ee6bf7abdc9bf35,0x3f80bf1d3f5cbf71,
0x3dfb3f313f223e48,0xbf583f73bedb3f78,0xbf7f3f13bf623f6d,0xbeb8befcbf4e3d49,0x3e89bf6abe95bf0e,0x3f7cbf423f3ebf7d,0x3f65be603f7fbf35,0xbcc93f4a3f043eac,
0xbf7b3f55bf353f80,0xbf0ebe48bf6d3ec4,0x3e483f0e3f350000,0xbf553f7bbec43f6d,0x3f7bbf553f35bf80,0x3f0e3e483f6dbec4,0xbe48bf0ebf350000,0x3f55bf7b3ec4bf6d,
0xbe48bf0ebf358000,0x3f55bf7b3ec4bf6d,0xbf7b3f55bf353f80,0xbf0ebe48bf6d3ec4,0x3e483f0e3f358000,0xbf553f7bbec43f6d,0x3f7bbf553f35bf80,0x3f0e3e483f6dbec4,
0x3f4abf803e95bf55,0x3f58bea13f80bf4e,0x3f42be2f3f7fbf35,0xbeb83f5f3e793edb,0xbf773f6abf223f7b,0xbf13bd97bf713f04,0xbee6be60bf623ec4,0x3f31bf7e3e16bf3e,
0x3f1d3cc93f75bf0e,0xbf093f733d493f18,0xbf273f7cbdc93f35,0xbf6f3efcbf783f67,0xbe89becfbf463e48,0x3f51bf7f3eacbf5c,0x3f65bf7a3ef1bf6d,0x3f39bdfb3f7dbf2c,
0xbf3e3f7dbe483f35,0xbf5c3edbbf7f3f62,0x3eac3e793f55bec4,0xbf4e3f80be953f46,0x3d49bf18bf0e0000,0x3f78bf713f22bf75,0xbf673f04bf7b3f6d,0x3e16bf2cbef1bdc9,
0xbf2c3e16bf7b3f35,0x3f04bf67bdc9bef1,0xbf713f78bf0e3f6d,0xbf183d49bf753f22,0x3f80bf4e3f55bf80,0x3e793eac3f46be95,0x3edbbf5cbe48bec4,0x3f7dbf3e3f62bf7f,
0x3f6abf7f3ef1bf55,0x3f1dbe2f3f78bf3e,0x3f58befc3f7fbf6d,0xbea13f393eac3e16,0x3cc93ee63f22be48,0xbf773f7abf183f67,0xbf513f7ebe953f35,0xbf423eb8bf803f5c,
0x3ecf3d973f62bf0e,0xbf4a3f7cbe793f2c,0xbf093f5f3dc93ec4,0xbf733f31bf713f7d,0xbf803f65bf463f7b,0xbe89be60bf4e3edb,0xbf133dfbbf753f35,0x3f27bf6f3d49bf04,
0x3f75bf463f6dbf80,0xbdc93ef13f0ebe48,0x3f62bf7f3ec4bf35,0x3f22be953f7bbf55,0x3e95bf22bec40000,0x3f7fbf623f55bf7b,0xbef13dc9bf6d3f35,0x3f46bf753e48bf0e,
0xbe953f223ec48000,0xbf7f3f62bf553f7b,0x3ef1bdc93f6dbf35,0xbf463f75be483f0e,0x3f75bf463f6dbf80,0xbdc93ef13f0ebe48,0x3f62bf7f3ec4bf35,0x3f22be953f7bbf55,
0xbf513f1dbf7f3f7b,0x3ee6bf31be79bd49,0xbeb83d97bf623f35,0x3f5fbf7a3eacbf18,0xbf583f77be953f0e,0xbf273ecfbf7d3f67,0xbf803f73bf463f6d,0xbdfbbe2fbf3e3f04,
0x3f13bf4abdc9be48,0x3f65bf393f78bf80,0x3f6fbf7f3ef1bf35,0x3efcbe603f71bf4e,0xbf093e89bf753f55,0x3f42bf6a3e16bedb,0x3cc9bea1bf223ec4,0x3f7ebf7c3f2cbf5c,
0x3e79bd493f55bf35,0xbf713f7dbef13f22,0x3f18bedb3f7bbf6d,0xbf3e3f5cbdc93e95,0xbf043f2c3e480000,0xbf673f4ebf753f7f,0xbe163eac3f0ebec4,0xbf803f78bf463f62,
0xbf783f80bf0e3f35,0xbeac3e16bf623f46,0xbf4e3f67be483ec4,0xbf2c3f04bf7f3f75,0xbf5c3f3ebf7b3f80,0x3edbbf18be953dc9,0xbf7d3f71bf553f6d,0x3d49be79bf223ef1,
0x3f42bf513dc9be48,0x3f31bf1d3f80bf7d,0x3f5fbf6a3e95bec4,0x3f09bee63f78bf71,0x3f73bf7a3ef1bf0e,0x3eb8be893f67bf5c,0x3f7ebf803f22bf35,0x3e2fbd973f4ebf3e,
0x3f27bf133f7fbf7b,0xbf393f4abd493e16,0x3efcbecf3f75bf6d,0xbf583f65be793eac,0x3ea1be603f62bf55,0xbf6f3f77bedb3f04,0x3dfbbcc93f46bf35,0xbf7c3f7fbf183f2c,
0x3f003f003f003f00,0x3f003f003f003f00,0x3f003f003f003f00,0x3f003f003f003f00,0x3f003f003f003f00,0x3f003f003f003f00,0x3f003f003f003f00,0x3f003f003f003f00,
0xbf00bf003f003f00,0xbf00bf003f003f00,0xbf00bf003f003f00,0xbf00bf003f003f00,0xbf00bf003f003f00,0xbf00bf003f003f00,0xbf00bf003f003f00,0xbf00bf003f003f00,
0x3ea13e603e953e48,0x3eb83e893eac3e79,0x3dfb3cc93dc90000,0x3e2f3d973e163d49,0x3f273f133f223f0e,0x3f313f1d3f2c3f18,0x3efc3ecf3ef13ec4,0x3f093ee63f043edb,
0x3f733f7a3f753f7b,0x3f6f3f773f713f78,0x3f7e3f803f7f3f80,0x3f7c3f7f3f7d3f80,0x3f423f513f463f55,0x3f393f4a3f3e3f4e,0x3f5f3f6a3f623f6d,0x3f583f653f5c3f67,
0xbf04bf2cbf0ebf35,0xbedbbf18bef1bf22,0xbe16beacbe48bec4,0xbd49be79bdc9be95,0xbf78bf80bf7bbf80,0xbf71bf7dbf75bf7f,0xbf4ebf67bf55bf6d,0xbf3ebf5cbf46bf62,
0x3f5c3f3e3f553f35,0x3f673f4e3f623f46,0x3f7d3f713f7b3f6d,0x3f803f783f7f3f75,0x3e793d493e488000,0x3eac3e163e953dc9,0x3f183edb3f0e3ec4,0x3f2c3f043f223ef1,
0xbf58bf77bf62bf7b,0xbf42bf6abf4ebf71,0xbf80bf73bf7fbf6d,0xbf7ebf7cbf80bf78,0xbf51bf1dbf46bf0e,0xbf65bf39bf5cbf2c,0xbeb8bd97be950000,0xbefcbe60bedbbe16,
0x3f093e893ef13e48,0x3f273ecf3f183eac,0xbcc9bea1bdc9bec4,0x3dfbbe2f3d49be79,0xbf13bf4abf22bf55,0xbee6bf31bf04bf3e,0xbf6fbf7fbf75bf80,0xbf5fbf7abf67bf7d,
0x3f623f7f3f6d3f80,0x3f463f753f553f7b,0x3e953f223ec43f35,0x3dc93ef13e483f0e,0xbef1bdc9bec40000,0xbf22be95bf0ebe48,0xbf75bf46bf6dbf35,0xbf7fbf62bf7bbf55,
0xbef1bdc9bec48000,0xbf22be95bf0ebe48,0xbf75bf46bf6dbf35,0xbf7fbf62bf7bbf55,0xbf62bf7fbf6dbf80,0xbf46bf75bf55bf7b,0xbe95bf22bec4bf35,0xbdc9bef1be48bf0e,
0x3f803f653f7f3f55,0x3f773f7a3f7d3f71,0x3f133dfb3ef10000,0x3f423eb83f2c3e79,0xbecf3d97be953e48,0xbf1dbe2fbf04bd49,0x3f093f5f3f223f6d,0x3ea13f393edb3f4e,
0xbcc93ee63dc93f0e,0xbe893e60be163eac,0x3f513f7e3f623f80,0x3f273f6f3f3e3f78,0xbf6abf7fbf75bf7b,0xbf4abf7cbf5cbf80,0xbf58befcbf46bec4,0xbf73bf31bf67bf18,
0x3f803f4e3f7b3f35,0x3f783f713f7f3f62,0x3edb3f5c3f0e3f6d,0x3e163f2c3e953f46,0xbf3ebf7dbf55bf80,0xbf04bf67bf22bf75,0x3eacbe793e48bec4,0x3f183d493ef1bdc9,
0x3d493f183e483f35,0xbe793eacbdc93ef1,0xbf67bf04bf55bec4,0xbf7dbf3ebf75bf22,0x3f2c3e163f0e8000,0x3f5c3edb3f463e95,0x3f713f783f7b3f6d,0x3f4e3f803f623f7f,
0x3f773f6a3f7f3f55,0x3f513f7f3f673f78,0x3ee6be603e95bec4,0x3f393dfb3f18bd49,0xbf4abf80bf62bf7b,0xbf09bf73bf2cbf7d,0xbf42be2fbf220000,0xbf6fbefcbf5cbeac,
0xbe893ecfbdc93f0e,0xbf133d97bedb3e79,0x3f653f7a3f753f6d,0x3f313f7e3f4e3f80,0x3f1dbcc93ef1be48,0x3f583ea13f3e3e16,0xbf27bf7cbf46bf80,0xbeb8bf5fbf04bf71,
0x3f0e3f7b3f353f80,0x3e483f553ec43f6d,0xbf55be48bf350000,0xbf7bbf0ebf6dbec4,0xbf0ebf7bbf35bf80,0xbe48bf55bec4bf6d,0x3f553e483f350000,0x3f7b3f0e3f6d3ec4,
0xbf55be48bf358000,0xbf7bbf0ebf6dbec4,0xbf0ebf7bbf35bf80,0xbe48bf55bec4bf6d,0x3f553e483f358000,0x3f7b3f0e3f6d3ec4,0x3f0e3f7b3f353f80,0x3e483f553ec43f6d,
0x3e893f6a3ef13f7b,0xbe2f3f273d493f4e,0x3f653e603f460000,0x3f803f1d3f783edb,0x3dfbbf31bdc9bf55,0x3f09bea13eacbf04,0xbf7fbf13bf75bec4,0xbf6fbf5fbf7dbf3e,
0xbf77becfbf62be48,0xbf7cbf42bf80bf18,0x3ee63f7a3f223f80,0x3cc93f4a3e793f67,0x3f7e3f393f7f3f0e,0x3f583f733f713f5c,0xbd97bf51be95bf6d,0x3eb8befc3e16bf2c,
0xbedb3f04be483f35,0xbf4e3d49bf223e95,0xbf2cbf7dbf55bf6d,0xbe79bf71bef1bf7f,0xbeacbf78bf0ebf80,0x3e16bf3ebdc9bf62,0x3f803f183f7b3ec4,0x3f5c3f673f753f46,
0xbf67bf5cbf7bbf35,0xbf18bf80bf46bf75,0x3f3ebe163f0ebec4,0x3f783eac3f623dc9,0x3f713e793f558000,0x3f7d3f2c3f7f3ef1,0xbd493f4e3e483f6d,0xbf043edbbe953f22,
0xbf80bee6bf75be48,0xbf5fbf58bf78bf2c,0x3f133f7e3f463f6d,0x3d973f6a3eac3f7d,0x3eb8bf273dc9bf55,0x3f4abe2f3f18bedb,0xbf7abe89bf620000,0xbf73bf39bf80bf04,
0xbcc9bf65be95bf7b,0x3efcbf093e79bf3e,0xbf513dfbbf223ec4,0xbf7fbecfbf71be16,0x3f6f3f423f7f3f0e,0x3f1d3f7c3f4e3f67,0xbe60bf77bef1bf80,0x3ea1bf313d49bf5c,
0x3dc93f753ec43f80,0xbef13f22be483f55,0xbf46bf62bf6dbf35,0xbe95bf7fbf0ebf7b,0x3f7f3e953f6d0000,0x3f623f463f7b3f0e,0xbf223ef1bec43f35,0xbf75bdc9bf553e48,
0xbf7fbe95bf6d8000,0xbf62bf46bf7bbf0e,0x3f22bef13ec4bf35,0x3f753dc93f55be48,0x3dc93f753ec43f80,0xbef13f22be483f55,0xbf46bf62bf6dbf35,0xbe95bf7fbf0ebf7b,
0xbf583e89bf223f0e,0xbf7fbeb8bf78bd49,0x3f803ea13f750000,0x3f4a3f513f713f18,0x3e2f3f7e3ef13f7b,0xbee63f39be163f67,0x3ecfbf423dc9bf6d,0x3f5fbe603f2cbf04,
0xbf09bf77bf46bf55,0x3d97bf6fbe79bf80,0xbcc93f733e953f80,0xbf1d3f13beac3f4e,0xbf7cbdfbbf623e48,0xbf65bf31bf7dbedb,0x3f6a3f273f7f3ec4,0x3efc3f7a3f3e3f5c,
0xbf18bf67bf55bf35,0x3d49bf78be95bf7f,0x3f5c3f2c3f7b3ec4,0x3eac3f7d3f223f62,0x3e16bf71be48bf80,0x3f3ebf043ef1bf46,0x3e793f803f0e3f6d,0xbedb3f4ebdc93f75,
0x3f4ebedb3f0ebf35,0x3f803e793f75bdc9,0xbf043f3ebe483f6d,0xbf713e16bf463ef1,0x3f7d3eac3f7b8000,0x3f2c3f5c3f623f22,0xbf783d49bf553ec4,0xbf67bf18bf7fbe95,
0x3f73be603f46bf0e,0x3f6a3efc3f803e16,0xbf7e3cc9bf623ec4,0xbf51bf27bf78beac,0x3f7f3e2f3f75be48,0x3f313f4a3f673f04,0xbf77beb8bf7f0000,0xbf09bf65bf4ebf2c,
0x3ea13f7a3f223f55,0xbecf3f5fbd493f7d,0xbdfbbf80bef1bf6d,0x3f13bf423e79bf71,0xbd973f7c3e953f7b,0xbf393f1dbedb3f5c,0x3e89bf6fbdc9bf80,0x3f58bee63f18bf3e,
0xbec43f6d00003f80,0xbf6d3ec4bf353f35,0x3ec4bf6d0000bf80,0x3f6dbec43f35bf35,0xbec43f6d00003f80,0xbf6d3ec4bf353f35,0x3ec4bf6d0000bf80,0x3f6dbec43f35bf35,
0xbf6dbec4bf808000,0xbec4bf6dbf35bf35,0x3f6d3ec43f808000,0x3ec43f6d3f353f35,0xbf6dbec4bf808000,0xbec4bf6dbf35bf35,0x3f6d3ec43f808000,0x3ec43f6d3f353f35,
0xbf42bf13bf75be48,0xbcc9bf7ebedbbf5c,0x3f5f3ecf3f7f0000,0x3e603f733f183f3e,0xbee6bf58bf46bf0e,0x3eb8bf77bd49bf7d,0x3f1d3f393f623ec4,0xbe2f3f7f3e793f71,
0x3f27bf513e95bf7b,0x3f80bdfb3f67bf04,0xbefc3f6abdc93f80,0xbf7a3ea1bf4e3f2c,0x3f65bf093f22bf55,0x3f6f3e893f80be16,0xbf4a3f31bef13f6d,0xbf7cbd97bf783eac,
0x3f7dbeac3f55bf35,0x3f3e3f043f753dc9,0xbf78bd49bf7b3ec4,0xbedbbf4ebf46bef1,0x3f18bf673e48bf80,0x3f80be793f62bf22,0xbf5c3f2cbf0e3f6d,0xbf71be16bf7f3e95,
0x3e163f713f0e3f35,0xbf2c3f5cbe953f7f,0x3e79bf80be48bf6d,0x3f67bf183f22bf62,0x3f4e3edb3f7b8000,0x3d493f783ef13f46,0xbf04bf3ebf55bec4,0x3eacbf7dbdc9bf75,
0xbf513f4abef13f7b,0xbf73bcc9bf7d3edb,0x3eb8bf7fbdc9bf6d,0x3f77bf093f3ebf5c,0x3e603f5f3f223f0e,0xbf273f6abe793f80,0xbf39bee6bf750000,0x3dfbbf7cbeacbf4e,
0xbf13bf1dbf62be48,0x3ea1bf80be16bf67,0x3f6f3d973f7fbec4,0x3e893f583f2c3f04,0xbf7a3efcbf463f55,0xbf42becfbf783d49,0x3f31bf653e95bf80,0x3f7ebe2f3f71bf18,
0xbf463f62bec43f80,0xbf753dc9bf7b3f0e,0x3f7fbe953f6dbf35,0x3ef13f223f553e48,0xbf22bef1bf6d0000,0x3e95bf7fbe48bf55,0xbdc93f753ec43f35,0xbf623f46bf0e3f7b,
0xbf22bef1bf6d8000,0x3e95bf7fbe48bf55,0xbdc93f753ec43f35,0xbf623f46bf0e3f7b,0x3f46bf623ec4bf80,0x3f75bdc93f7bbf0e,0xbf7f3e95bf6d3f35,0xbef1bf22bf55be48,
0x3ecfbf7fbdc9bf55,0x3f7ebf133f4ebf67,0x3f093efc3f620000,0xbee63f803d493f5c,0x3f313ea13f75be48,0xbe893f7a3e793f3e,0xbf7c3f1dbf463f6d,0xbf27beb8bf713e16,
0x3f6abd973f7fbf0e,0x3dfb3f513f183edb,0xbf583f5fbef13f80,0xbf653cc9bf803f04,0xbf393f73be953f7b,0xbf773e60bf783f2c,0xbe2fbf4abf22bec4,0x3f42bf6f3eacbf7d,
0xbeac3f783e483f35,0xbf7d3f2cbf463f75,0x3f80bf183f55bf6d,0x3f043edb3f62bdc9,0x3f67bf5c3f0ebf80,0x3f4e3d493f7fbef1,0xbf3ebe16bf7b3ec4,0x3e79bf71be95bf22,
0xbf713e79bf7b3f35,0xbe16bf3ebf22be95,0x3d493f4e3f0e3ec4,0xbf5c3f67bef13f7f,0x3edb3f043f558000,0xbf183f80bdc93f62,0x3f2cbf7d3e48bf6d,0x3f78beac3f75bf46,
0x3f1dbf803dc9bf55,0x3f7abee63f71bf5c,0x3f273e2f3f75bec4,0xbecf3f773e163f2c,0xbf5f3f6fbef13f7b,0xbf513d97bf803f18,0xbea1bf09bf460000,0x3f39bf7e3e79bf67,
0x3f4abcc93f7fbf0e,0xbe603f653eac3f04,0xbf423f7cbe953f6d,0xbf6a3e89bf7d3f3e,0xbefcbeb8bf623e48,0x3f13bf7f3d49bf4e,0x3f73bf583f22bf80,0x3f313dfb3f78bedb,
0xbf7b3f55bf353f80,0xbf0ebe48bf6d3ec4,0x3e483f0e3f350000,0xbf553f7bbec43f6d,0x3f7bbf553f35bf80,0x3f0e3e483f6dbec4,0xbe48bf0ebf350000,0x3f55bf7b3ec4bf6d,
0xbe48bf0ebf358000,0x3f55bf7b3ec4bf6d,0xbf7b3f55bf353f80,0xbf0ebe48bf6d3ec4,0x3e483f0e3f358000,0xbf553f7bbec43f6d,0x3f7bbf553f35bf80,0x3f0e3e483f6dbec4,
0x3f7ebf313f62bf7b,0x3e603ee63f3ebe16,0x3d973f133f220000,0xbf6a3f77bf043f71,0xbf5f3eb8bf7f3f55,0x3e2fbf42bedbbe79,0x3ea1bf58be95bec4,0x3f80bf4a3f4ebf80,
0xbdfb3f393ef13e48,0xbf7a3f65bf2c3f7d,0xbf7f3f51bf463f80,0xbecfbe89bf5c3eac,0x3efcbf6fbdc9bf0e,0x3f7cbf273f67bf78,0x3f73bf093f75bf6d,0x3cc93f1d3f183d49,
0xbf2c3e16bf7b3f35,0x3f04bf67bdc9bef1,0xbf713f78bf0e3f6d,0xbf183d49bf753f22,0x3f80bf4e3f55bf80,0x3e793eac3f46be95,0x3edbbf5cbe48bec4,0x3f7dbf3e3f62bf7f,
0x3f3ebf7d3e48bf35,0x3f5cbedb3f7fbf62,0xbeacbe79bf553ec4,0x3f4ebf803e95bf46,0xbd493f183f0e8000,0xbf783f71bf223f75,0x3f67bf043f7bbf6d,0xbe163f2c3ef13dc9,
0xbeb83f423e953e48,0xbf7e3f51bf5c3f80,0xbf7a3f77bf223f6d,0xbee6bcc9bf673f18,0xbf393ea1bf7f3f55,0x3efcbf58be16beac,0x3e2fbf1dbef10000,0x3f7fbf6a3f3ebf78,
0xbf6f3f27bf753f7b,0x3dfbbf13bf043d49,0xbe60be89bf463ec4,0x3f65bf803edbbf4e,0x3f31bf733dc9bf0e,0x3f5fbf093f7dbf71,0x3f7cbf4a3f62bf80,0x3d973ecf3f2cbe79,
0xbf753f46bf6d3f80,0x3dc9bef1bf0e3e48,0xbf623f7fbec43f35,0xbf223e95bf7b3f55,0xbe953f223ec40000,0xbf7f3f62bf553f7b,0x3ef1bdc93f6dbf35,0xbf463f75be483f0e,
0x3e95bf22bec48000,0x3f7fbf623f55bf7b,0xbef13dc9bf6d3f35,0x3f46bf753e48bf0e,0xbf753f46bf6d3f80,0x3dc9bef1bf0e3e48,0xbf623f7fbec43f35,0xbf223e95bf7b3f55,
0x3e2f3dfb3f46bf0e,0xbf733f80bf043f3e,0xbecf3f273e950000,0xbf773f58bf673f7d,0x3f7abf5f3f62bf7b,0xbd973eb83f18beac,0x3f31bee63f7fbf6d,0xbf1d3f513d493e79,
0xbf7c3f7ebf223f55,0xbea13cc9bf5c3f2c,0xbf6a3f42bf753f80,0x3e89bf09bedb3e16,0xbe603efc3ef1be48,0xbf7f3f6fbf4e3f71,0xbf393f65bdc93ec4,0xbf4a3f13bf803f78,
0x3f78bf803f0ebf35,0x3eacbe163f62bf46,0x3f4ebf673e48bec4,0x3f2cbf043f7fbf75,0x3f5cbf3e3f7bbf80,0xbedb3f183e95bdc9,0x3f7dbf713f55bf6d,0xbd493e793f22bef1,
0x3e79bd493f55bf35,0xbf713f7dbef13f22,0x3f18bedb3f7bbf6d,0xbf3e3f5cbdc93e95,0xbf043f2c3e488000,0xbf673f4ebf753f7f,0xbe163eac3f0ebec4,0xbf803f78bf463f62,
0x3d97be2fbf223f0e,0x3f80bf7e3f3ebf4e,0x3e89beb8bef13ec4,0x3f7abf733f5cbf67,0x3ee6bf09be953e48,0x3f6abf5f3f71bf78,0x3f1dbf31bdc90000,0x3f51bf423f7dbf80,
0x3f7fbf7c3f46bf55,0xbcc93dfb3f2cbf18,0x3f77bf6f3f62bf6d,0xbe603ea13f04bedb,0x3f65bf583f75bf7b,0xbecf3efc3eacbe79,0x3f4abf393f7fbf80,0xbf133f273e16bd49,
0x3f003f003f003f00,0x3f003f003f003f00,0x3f003f003f003f00,0x3f003f003f003f00,0x3f003f003f003f00,0x3f003f003f003f00,0x3f003f003f003f00,0x3f003f003f003f00,
0xbf00bf003f003f00,0xbf00bf003f003f00,0xbf00bf003f003f00,0xbf00bf003f003f00,0xbf00bf003f003f00,0xbf00bf003f003f00,0xbf00bf003f003f00,0xbf00bf003f003f00,
0x3f653f583f623f55,0x3f6a3f5f3f673f5c,0x3f4a3f393f463f35,0x3f513f423f4e3f3e,0x3f7f3f7c3f7f3f7b,0x3f803f7e3f803f7d,0x3f773f6f3f753f6d,0x3f7a3f733f783f71,
0x3ee63f093ef13f0e,0x3ecf3efc3edb3f04,0x3f1d3f313f223f35,0x3f133f273f183f2c,0x3d973e2f3dc93e48,0x3cc93dfb3d493e16,0x3e893eb83e953ec4,0x3e603ea13e793eac,
0x3f5c3f3e3f553f35,0x3f673f4e3f623f46,0x3f7d3f713f7b3f6d,0x3f803f783f7f3f75,0x3e793d493e480000,0x3eac3e163e953dc9,0x3f183edb3f0e3ec4,0x3f2c3f043f223ef1,
0x3f043f2c3f0e3f35,0x3edb3f183ef13f22,0x3e163eac3e483ec4,0x3d493e793dc93e95,0x3f783f803f7b3f80,0x3f713f7d3f753f7f,0x3f4e3f673f553f6d,0x3f3e3f5c3f463f62,
0x3f7a3f5f3f753f55,0x3f7f3f6f3f7d3f67,0x3f313ee63f223ec4,0x3f4a3f133f3e3f04,0x3e2fbdfb3dc9be48,0x3ea13cc93e79bd49,0xbecfbf27bef1bf35,0xbe89bf09beacbf18,
0x3e603efc3e953f0e,0x3d973eb83e163edb,0x3f393f653f463f6d,0x3f1d3f513f2c3f5c,0x3f7c3f7e3f7f3f7b,0x3f733f803f783f80,0x3f6a3f423f623f35,0x3f773f583f713f4e,
0xbf62bf7fbf6dbf80,0xbf46bf75bf55bf7b,0xbe95bf22bec4bf35,0xbdc9bef1be48bf0e,0x3ef13dc93ec40000,0x3f223e953f0e3e48,0x3f753f463f6d3f35,0x3f7f3f623f7b3f55,
0x3ef13dc93ec48000,0x3f223e953f0e3e48,0x3f753f463f6d3f35,0x3f7f3f623f7b3f55,0x3f623f7f3f6d3f80,0x3f463f753f553f7b,0x3e953f223ec43f35,0x3dc93ef13e483f0e,
0xbf31bf73bf46bf7b,0xbefcbf58bf18bf67,0xbf7cbf4abf75bf35,0xbf7fbf6abf80bf5c,0x3f6f3f273f623f0e,0x3f7e3f513f783f3e,0x3e60be893dc9bec4,0x3ee6bcc93eacbe16,
0x3f393ea13f223e48,0x3f5f3f093f4e3edb,0xbe2fbf1dbe95bf35,0x3d97becfbd49bf04,0x3eb83f423ef13f55,0x3dfb3f133e793f2c,0x3f7a3f773f7f3f6d,0x3f653f803f713f7d,
0xbd49bf18be48bf35,0x3e79beac3dc9bef1,0x3f673f043f553ec4,0x3f7d3f3e3f753f22,0xbf2cbe16bf0e0000,0xbf5cbedbbf46be95,0xbf71bf78bf7bbf6d,0xbf4ebf80bf62bf7f,
0x3f803f4e3f7b3f35,0x3f783f713f7f3f62,0x3edb3f5c3f0e3f6d,0x3e163f2c3e953f46,0xbf3ebf7dbf55bf80,0xbf04bf67bf22bf75,0x3eacbe793e48bec4,0x3f183d493ef1bdc9,
0x3f5f3eb83f463e48,0x3f7c3f273f713f04,0xbea1bf58bef1bf6d,0x3cc9bf1dbe16bf3e,0xbf7ebf31bf75bf0e,0xbf7abf65bf80bf4e,0xbd973f133dc93f35,0xbecf3e89be793edb,
0x3efc3f6f3f223f7b,0x3e2f3f423eac3f5c,0x3f733f093f623ec4,0x3f803f4a3f7d3f2c,0xbdfbbf39be95bf55,0x3e60bee63d49bf18,0xbf7fbf51bf7fbf35,0xbf6abf77bf78bf67,
0x3f0e3f7b3f353f80,0x3e483f553ec43f6d,0xbf55be48bf350000,0xbf7bbf0ebf6dbec4,0xbf0ebf7bbf35bf80,0xbe48bf55bec4bf6d,0x3f553e483f350000,0x3f7b3f0e3f6d3ec4,
0xbf55be48bf358000,0xbf7bbf0ebf6dbec4,0xbf0ebf7bbf35bf80,0xbe48bf55bec4bf6d,0x3f553e483f358000,0x3f7b3f0e3f6d3ec4,0x3f0e3f7b3f353f80,0x3e483f553ec43f6d,
0xbefc3eb8be953f0e,0xbf51bd97bf2c3e16,0x3f733f583f7f3f35,0x3f393f7e3f5c3f71,0x3f4a3cc93f22be48,0x3f7a3ee63f673e79,0xbf42bf7cbf62bf6d,0xbecfbf77bf18bf80,
0xbf5fbf6fbf75bf55,0xbf13bf7fbf3ebf7d,0xbea13f09bdc93f35,0xbf313dfbbf043eac,0x3f1d3f803f463f7b,0x3e603f653edb3f78,0x3f27be2f3ef1bec4,0x3f6a3e893f4e3d49,
0xbf67bf5cbf7bbf35,0xbf18bf80bf46bf75,0x3f3ebe163f0ebec4,0x3f783eac3f623dc9,0x3f713e793f550000,0x3f7d3f2c3f7f3ef1,0xbd493f4e3e483f6d,0xbf043edbbe953f22,
0x3edbbf043e48bf35,0x3f4ebd493f22be95,0x3f2c3f7d3f553f6d,0x3e793f713ef13f7f,0x3eac3f783f0e3f80,0xbe163f3e3dc93f62,0xbf80bf18bf7bbec4,0xbf5cbf67bf75bf46,
0x3f31bea13ef1bf0e,0x3f773e603f5cbd49,0xbf7cbf1dbf7fbec4,0xbf42bf6fbf67bf4e,0x3ecf3f7f3f223f7b,0xbdfb3f513e163f71,0x3f09befc3e95bf35,0x3f653cc93f3ebe79,
0x3f393f733f623f55,0x3e893f7a3f043f80,0x3e2fbf4abdc9bf6d,0x3f27beb83edbbf18,0xbf6abd97bf463e48,0xbf7ebf13bf7dbeac,0x3f583f5f3f753f35,0x3ee63f803f2c3f78,
0xbdc9bf75bec4bf80,0x3ef1bf223e48bf55,0x3f463f623f6d3f35,0x3e953f7f3f0e3f7b,0xbf7fbe95bf6d0000,0xbf62bf46bf7bbf0e,0x3f22bef13ec4bf35,0x3f753dc93f55be48,
0x3f7f3e953f6d8000,0x3f623f463f7b3f0e,0xbf223ef1bec43f35,0xbf75bdc9bf553e48,0xbdc9bf75bec4bf80,0x3ef1bf223e48bf55,0x3f463f623f6d3f35,0x3e953f7f3f0e3f7b,
0x3f7a3efc3f7f3e48,0x3f273f6a3f5c3f3e,0xbf31bf65bf62bf35,0xbdfbbf7cbedbbf7d,0x3f13bf1d3e95bf55,0x3f73bcc93f4ebeac,0xbf6f3d97bf463ec4,0xbf77bf09bf80be79,
0xbe603f5f3dc93f7b,0xbf423ecfbf043f2c,0x3f39bee63ef1bf35,0x3f7e3e2f3f67be16,0x3f513f4a3f753f0e,0x3ea13f803f183f71,0xbeb8bf7fbf22bf6d,0x3e89bf58bd49bf78,
0xbf4e3edbbf0e3f35,0xbf80be79bf753dc9,0x3f04bf3e3e48bf6d,0x3f71be163f46bef1,0xbf7dbeacbf7b0000,0xbf2cbf5cbf62bf22,0x3f78bd493f55bec4,0x3f673f183f7f3e95,
0xbf18bf67bf55bf35,0x3d49bf78be95bf7f,0x3f5c3f2c3f7b3ec4,0x3eac3f7d3f223f62,0x3e16bf71be48bf80,0x3f3ebf043ef1bf46,0x3e793f803f0e3f6d,0xbedb3f4ebdc93f75,
0x3ee6bf583dc9bf7b,0x3f6fbe893f3ebf18,0xbf1d3f39be953f6d,0xbf7c3d97bf5c3edb,0x3f42bf133ef1bf55,0x3f803dfb3f71be79,0xbf5f3ecfbf223f35,0xbf7abea1bf7d3d49,
0x3f653f093f7f3e48,0x3eb83f773f2c3f4e,0xbf4abf31bf75bec4,0xbe2fbf7fbf04bf67,0x3f273f513f623f0e,0xbcc93f7e3eac3f78,0xbefcbf6abf46bf35,0x3e60bf73be16bf80,
0xbec43f6d00003f80,0xbf6d3ec4bf353f35,0x3ec4bf6d0000bf80,0x3f6dbec43f35bf35,0xbec43f6d00003f80,0xbf6d3ec4bf353f35,0x3ec4bf6d0000bf80,0x3f6dbec43f35bf35,
0xbf6dbec4bf808000,0xbec4bf6dbf35bf35,0x3f6d3ec43f808000,0x3ec43f6d3f353f35,0xbf6dbec4bf808000,0xbec4bf6dbf35bf35,0x3f6d3ec43f808000,0x3ec43f6d3f353f35,
0xbd97bf7cbef1bf55,0x3f31bf4a3eacbf78,0x3e893f6f3f223f35,0xbf093f65be163f80,0x3ea1bf7abdc9bf7b,0x3f6abefc3f2cbf4e,0xbdfb3f803e953f6d,0xbf513f27bf043f67,
0x3f7fbe2f3f62bf0e,0x3f393f1d3f713e79,0xbf773eb8bf463f35,0xbf58bee6bf7dbd49,0x3f733e603f7fbe48,0x3ecf3f5f3f3e3f18,0xbf7ebcc9bf753ec4,0xbf13bf42bf5cbedb,
0x3e163f713f0e3f35,0xbf2c3f5cbe953f7f,0x3e79bf80be48bf6d,0x3f67bf183f22bf62,0x3f4e3edb3f7b0000,0x3d493f783ef13f46,0xbf04bf3ebf55bec4,0x3eacbf7dbdc9bf75,
0xbf7d3eacbf553f35,0xbf3ebf04bf75bdc9,0x3f783d493f7bbec4,0x3edb3f4e3f463ef1,0xbf183f67be483f80,0xbf803e79bf623f22,0x3f5cbf2c3f0ebf6d,0x3f713e163f7fbe95,
0x3e2fbf7ebe95bf55,0x3f65bf313f18bf71,0x3ecf3f423f463ec4,0xbefc3f7abd493f78,0xbf58be89bf7f3e48,0xbd97bf6fbf04bf2c,0x3f80bea13f62bf35,0x3f1d3f133f673e16,
0x3f7cbdfb3f75bf0e,0x3ee63f393f4e3eac,0xbf6a3f27bf223f6d,0xbf5fbe60bf803e79,0x3f09bf773dc9bf7b,0x3f7fbeb83f5cbf3e,0x3cc93f733ef13f35,0xbf4a3f51bedb3f7d,
0x3f46bf623ec4bf80,0x3f75bdc93f7bbf0e,0xbf7f3e95bf6d3f35,0xbef1bf22bf55be48,0x3f223ef13f6d0000,0xbe953f7f3e483f55,0x3dc9bf75bec4bf35,0x3f62bf463f0ebf7b,
0x3f223ef13f6d8000,0xbe953f7f3e483f55,0x3dc9bf75bec4bf35,0x3f62bf463f0ebf7b,0xbf463f62bec43f80,0xbf753dc9bf7b3f0e,0x3f7fbe953f6dbf35,0x3ef13f223f553e48,
0xbf6f3f42bf223f7b,0xbf4abe2fbf7d3eac,0x3e60bf77be95bf35,0x3f73bf393f2cbf78,0x3cc9bf65bef1bf0e,0x3f5fbf583f04bf80,0x3f513dfb3f7fbec4,0xbd973f6a3edb3f18,
0xbeb8bf27bf46be48,0x3f1dbf7c3e16bf71,0x3f7abe893f75bf35,0x3ea13f313f3e3e79,0x3f80bee63f62bf55,0x3efc3f093f5c3d49,0xbf133f7ebdc93f6d,0xbf7f3ecfbf673f4e,
0x3f71be793f7bbf35,0x3e163f3e3f223e95,0xbd49bf4ebf0ebec4,0x3f5cbf673ef1bf7f,0xbedbbf04bf550000,0x3f18bf803dc9bf62,0xbf2c3f7dbe483f6d,0xbf783eacbf753f46,
0xbeac3f783e483f35,0xbf7d3f2cbf463f75,0x3f80bf183f55bf6d,0x3f043edb3f62bdc9,0x3f67bf5c3f0ebf80,0x3f4e3d493f7fbef1,0xbf3ebe16bf7b3ec4,0x3e79bf71be95bf22,
0xbdfbbf31bf22be48,0x3f58bf733edbbf78,0x3f7fbf133f62bf6d,0x3eb83efc3f4ebd49,0xbe893f6a3e953f0e,0xbf7c3f42bf3e3f7d,0xbf653e60bf7f3f35,0x3cc9bf4abf04beac,
0x3f7ebf393f46bf7b,0x3f093ea13f67be79,0xbd973f513ef13ec4,0xbf6f3f5fbf183f80,0xbf773ecfbf753f55,0xbe2fbf27bf2cbe16,0x3ee6bf7abdc9bf35,0x3f80bf1d3f5cbf71,
0xbf7b3f55bf353f80,0xbf0ebe48bf6d3ec4,0x3e483f0e3f350000,0xbf553f7bbec43f6d,0x3f7bbf553f35bf80,0x3f0e3e483f6dbec4,0xbe48bf0ebf350000,0x3f55bf7b3ec4bf6d,
0xbe48bf0ebf358000,0x3f55bf7b3ec4bf6d,0xbf7b3f55bf353f80,0xbf0ebe48bf6d3ec4,0x3e483f0e3f358000,0xbf553f7bbec43f6d,0x3f7bbf553f35bf80,0x3f0e3e483f6dbec4,
0x3f1d3cc93f75bf0e,0xbf093f733d493f18,0xbf273f7cbdc93f35,0xbf6f3efcbf783f67,0xbe89becfbf463e48,0x3f51bf7f3eacbf5c,0x3f65bf7a3ef1bf6d,0x3f39bdfb3f7dbf2c,
0xbf4a3f80be953f55,0xbf583ea1bf803f4e,0xbf423e2fbf7f3f35,0x3eb8bf5fbe79bedb,0x3f77bf6a3f22bf7b,0x3f133d973f71bf04,0x3ee63e603f62bec4,0xbf313f7ebe163f3e,
0x3f3ebf7d3e48bf35,0x3f5cbedb3f7fbf62,0xbeacbe79bf553ec4,0x3f4ebf803e95bf46,0xbd493f183f0e0000,0xbf783f71bf223f75,0x3f67bf043f7bbf6d,0xbe163f2c3ef13dc9,
0x3f2cbe163f7bbf35,0xbf043f673dc93ef1,0x3f71bf783f0ebf6d,0x3f18bd493f75bf22,0xbf803f4ebf553f80,0xbe79beacbf463e95,0xbedb3f5c3e483ec4,0xbf7d3f3ebf623f7f,
0xbecfbd97bf623f0e,0x3f4abf7c3e79bf2c,0x3f09bf5fbdc9bec4,0x3f73bf313f71bf7d,0x3f80bf653f46bf7b,0x3e893e603f4ebedb,0x3f13bdfb3f75bf35,0xbf273f6fbd493f04,
0x3f6abf7f3ef1bf55,0x3f1dbe2f3f78bf3e,0x3f58befc3f7fbf6d,0xbea13f393eac3e16,0x3cc93ee63f22be48,0xbf773f7abf183f67,0xbf513f7ebe953f35,0xbf423eb8bf803f5c,
0x3f75bf463f6dbf80,0xbdc93ef13f0ebe48,0x3f62bf7f3ec4bf35,0x3f22be953f7bbf55,0x3e95bf22bec40000,0x3f7fbf623f55bf7b,0xbef13dc9bf6d3f35,0x3f46bf753e48bf0e,
0xbe953f223ec48000,0xbf7f3f62bf553f7b,0x3ef1bdc93f6dbf35,0xbf463f75be483f0e,0x3f75bf463f6dbf80,0xbdc93ef13f0ebe48,0x3f62bf7f3ec4bf35,0x3f22be953f7bbf55,
0x3f13bf4abdc9be48,0x3f65bf393f78bf80,0x3f6fbf7f3ef1bf35,0x3efcbe603f71bf4e,0xbf093e89bf753f55,0x3f42bf6a3e16bedb,0x3cc9bea1bf223ec4,0x3f7ebf7c3f2cbf5c,
0x3f51bf1d3f7fbf7b,0xbee63f313e793d49,0x3eb8bd973f62bf35,0xbf5f3f7abeac3f18,0x3f58bf773e95bf0e,0x3f27becf3f7dbf67,0x3f80bf733f46bf6d,0x3dfb3e2f3f3ebf04,
0xbe793d49bf553f35,0x3f71bf7d3ef1bf22,0xbf183edbbf7b3f6d,0x3f3ebf5c3dc9be95,0x3f04bf2cbe480000,0x3f67bf4e3f75bf7f,0x3e16beacbf0e3ec4,0x3f80bf783f46bf62,
0x3f78bf803f0ebf35,0x3eacbe163f62bf46,0x3f4ebf673e48bec4,0x3f2cbf043f7fbf75,0x3f5cbf3e3f7bbf80,0xbedb3f183e95bdc9,0x3f7dbf713f55bf6d,0xbd493e793f22bef1,
0xbf273f13bf7f3f7b,0x3f39bf4a3d49be16,0xbefc3ecfbf753f6d,0x3f58bf653e79beac,0xbea13e60bf623f55,0x3f6fbf773edbbf04,0xbdfb3cc9bf463f35,0x3f7cbf7f3f18bf2c,
0x3f42bf513dc9be48,0x3f31bf1d3f80bf7d,0x3f5fbf6a3e95bec4,0x3f09bee63f78bf71,0x3f73bf7a3ef1bf0e,0x3eb8be893f67bf5c,0x3f7ebf803f22bf35,0x3e2fbd973f4ebf3e,
0x3f803f80,0xbf80bf80,0x3f803f80,0xbf80bf80,0x3f803f80,0xbf80bf80,0x3f803f80,0xbf80bf80,
0xbf80bf8080008000,0x3f803f8080008000,0xbf80bf8080008000,0x3f803f8080008000,0xbf80bf8080008000,0x3f803f8080008000,0xbf80bf8080008000,0x3f803f8080008000,
0xbea1be603f753f7b,0x3eb83e89bf71bf78,0xbdfbbcc93f7f3f80,0x3e2f3d97bf7dbf80,0xbf27bf133f463f55,0x3f313f1dbf3ebf4e,0xbefcbecf3f623f6d,0x3f093ee6bf5cbf67,
0xbf73bf7abe95be48,0x3f6f3f773eac3e79,0xbf7ebf80bdc98000,0x3f7c3f7f3e163d49,0xbf42bf51bf22bf0e,0x3f393f4a3f2c3f18,0xbf5fbf6abef1bec4,0x3f583f653f043edb,
0xbf5cbf3e3f0e3f35,0x3f673f4ebef1bf22,0xbf7dbf713e483ec4,0x3f803f78bdc9be95,0xbe79bd493f7b3f80,0x3eac3e16bf75bf7f,0xbf18bedb3f553f6d,0x3f2c3f04bf46bf62,
0xbf04bf2cbf55bf35,0x3edb3f183f623f46,0xbe16beacbf7bbf6d,0x3d493e793f7f3f75,0xbf78bf80be488000,0x3f713f7d3e953dc9,0xbf4ebf67bf0ebec4,0x3f3e3f5c3f223ef1,
0xbf58bf77bef1be48,0x3f423f6a3f183eac,0xbf80bf733dc93ec4,0x3f7e3f7c3d49be79,0xbf51bf1d3f223f55,0x3f653f39bf04bf3e,0xbeb8bd973f753f80,0x3efc3e60bf67bf7d,
0x3f093e89bf62bf7b,0xbf27becf3f4e3f71,0xbcc9bea1bf7fbf6d,0xbdfb3e2f3f803f78,0xbf13bf4abf46bf0e,0x3ee63f313f5c3f2c,0xbf6fbf7fbe958000,0x3f5f3f7a3edb3e16,
0xbef1bdc93f6d3f80,0x3f223e95bf55bf7b,0xbf75bf463ec43f35,0x3f7f3f62be48bf0e,0xbf62bf7fbec40000,0x3f463f753f0e3e48,0xbe95bf22bf6dbf35,0x3dc93ef13f7b3f55,
0xbf62bf7fbec48000,0x3f463f753f0e3e48,0xbe95bf22bf6dbf35,0x3dc93ef13f7b3f55,0x3ef13dc9bf6dbf80,0xbf22be953f553f7b,0x3f753f46bec4bf35,0xbf7fbf623e483f0e,
0xbf80bf653dc93f0e,0x3f773f7a3e16beac,0xbf13bdfb3f623f80,0x3f423eb8bf3ebf78,0x3ecfbd97bf75bf7b,0xbf1dbe2f3f5c3f80,0xbf09bf5fbf46bec4,0x3ea13f393f673f18,
0x3cc9bee6bf7fbf55,0xbe893e603f7d3f71,0xbf51bf7ebef18000,0x3f273f6f3f2c3e79,0x3f6a3f7f3e95be48,0xbf4abf7cbf04bd49,0x3f583efcbf22bf6d,0xbf73bf313edb3f4e,
0xbd49bf18bf7bbf35,0xbe793eac3f7f3f62,0x3f673f04bf0ebf6d,0xbf7dbf3e3e953f46,0xbf2cbe163f553f80,0x3f5c3edbbf22bf75,0xbf71bf78be483ec4,0x3f4e3f803ef1bdc9,
0x3f803f4ebe48bf35,0xbf78bf71bdc93ef1,0x3edb3f5c3f553ec4,0xbe16bf2cbf75bf22,0xbf3ebf7dbf0e8000,0x3f043f673f463e95,0x3eacbe79bf7bbf6d,0xbf18bd493f623f7f,
0x3f773f6a3dc9bf0e,0xbf51bf7fbedb3e79,0x3ee6be60bf75bf6d,0xbf39bdfb3f4e3f80,0xbf4abf80bef13e48,0x3f093f733f3e3e16,0xbf42be2f3f463f80,0x3f6f3efcbf04bf71,
0xbe893ecf3f7f3f55,0x3f13bd97bf67bf78,0x3f653f7a3e95bec4,0xbf31bf7ebf183d49,0x3f1dbcc9bf62bf7b,0xbf58bea13f2c3f7d,0xbf27bf7cbf228000,0x3eb83f5f3f5c3eac,
0xbf55be483f353f80,0x3f7b3f0ebec4bf6d,0xbf0ebf7bbf350000,0x3e483f553f6d3ec4,0x3f553e48bf35bf80,0xbf7bbf0e3ec43f6d,0x3f0e3f7b3f350000,0xbe48bf55bf6dbec4,
0xbf0ebf7bbf358000,0x3e483f553f6d3ec4,0x3f553e48bf35bf80,0xbf7bbf0e3ec43f6d,0x3f0e3f7b3f358000,0xbe48bf55bf6dbec4,0xbf55be483f353f80,0x3f7b3f0ebec4bf6d,
0xbe89bf6abf62be48,0xbe2f3f273f803f18,0xbf65be603f223f80,0x3f803f1dbe79bf67,0xbdfb3f313f7f3f0e,0x3f09bea1bf71bf5c,0x3f7f3f13be95bf6d,0xbf6fbf5fbe163f2c,
0x3f773ecfbef1bf7b,0xbf7cbf423d493f4e,0xbee6bf7abf468000,0x3cc93f4a3f783edb,0xbf7ebf393dc93f55,0x3f583f733eacbf04,0x3d973f513f753ec4,0x3eb8befcbf7dbf3e,
0x3f673f5c3e48bf35,0xbf18bf80bf223e95,0xbf3e3e163f553f6d,0x3f783eacbef1bf7f,0xbf71be793f0e3f80,0x3f7d3f2cbdc9bf62,0x3d49bf4ebf7bbec4,0xbf043edb3f753f46,
0xbedb3f043f7b3f35,0x3f4ebd49bf46bf75,0xbf2cbf7dbf0e3ec4,0x3e793f713f623dc9,0xbeacbf78bf558000,0xbe163f3e3f7f3ef1,0x3f803f18be48bf6d,0xbf5cbf67be953f22,
0xbf80bee63e953f7b,0x3f5f3f583e79bf3e,0x3f133f7e3f22bec4,0xbd97bf6abf71be16,0x3eb8bf27bf7fbf0e,0xbf4a3e2f3f4e3f67,0xbf7abe893ef13f80,0x3f733f393d49bf5c,
0xbcc9bf65bf75be48,0xbefc3f093f783f2c,0xbf513dfb3f463f6d,0x3f7f3ecfbeacbf7d,0x3f6f3f423dc9bf55,0xbf1dbf7cbf183edb,0xbe60bf77bf628000,0xbea13f313f803f04,
0xbf7fbe953ec43f80,0x3f623f463e48bf55,0x3f22bef1bf6dbf35,0xbf75bdc93f0e3f7b,0x3dc93f753f6d0000,0x3ef1bf22bf7bbf0e,0xbf46bf62bec43f35,0x3e953f7f3f55be48,
0xbdc9bf75bf6d8000,0xbef13f223f7b3f0e,0x3f463f623ec4bf35,0xbe95bf7fbf553e48,0xbf7fbe953ec43f80,0x3f623f463e48bf55,0x3f22bef1bf6dbf35,0xbf75bdc93f0e3f7b,
0x3f58be89bf46bf55,0xbf7fbeb83e793f80,0xbf80bea13e953f80,0x3f4a3f513eacbf4e,0xbe2fbf7ebf623e48,0xbee63f393f7d3edb,0xbecf3f423f7f3ec4,0x3f5fbe60bf3ebf5c,
0x3f093f773f22bf0e,0x3d97bf6fbf78bd49,0x3cc9bf73bf758000,0xbf1d3f133f713f18,0x3f7c3dfbbef1bf7b,0xbf65bf31be163f67,0xbf6abf27bdc93f6d,0x3efc3f7a3f2cbf04,
0xbf4e3edb3f553f35,0x3f803e79be95bf7f,0x3f04bf3ebf7bbec4,0xbf713e163f223f62,0xbf7dbeac3e483f80,0x3f2c3f5c3ef1bf46,0x3f78bd49bf0ebf6d,0xbf67bf18bdc93f75,
0xbf18bf67bf0e3f35,0xbd493f783f75bdc9,0x3f5c3f2c3e48bf6d,0xbeacbf7dbf463ef1,0x3e16bf71bf7b8000,0xbf3e3f043f623f22,0x3e793f803f55bec4,0x3edbbf4ebf7fbe95,
0x3f73be60bf22bf55,0xbf6abefcbd493f7d,0xbf7e3cc93ef13f6d,0x3f513f273e79bf71,0x3f7f3e2fbe95bf7b,0xbf31bf4abedb3f5c,0xbf77beb83dc93f80,0x3f093f653f18bf3e,
0x3ea13f7a3f46bf0e,0x3ecfbf5fbf80be16,0xbdfbbf80bf623ec4,0xbf133f423f783eac,0xbd973f7c3f75be48,0x3f39bf1dbf67bf04,0x3e89bf6fbf7f8000,0xbf583ee63f4e3f2c,
0xbf6dbec400003f80,0x3ec43f6d3f35bf35,0x3f6d3ec40000bf80,0xbec4bf6dbf353f35,0xbf6dbec400003f80,0x3ec43f6d3f35bf35,0x3f6d3ec40000bf80,0xbec4bf6dbf353f35,
0x3ec4bf6dbf808000,0xbf6d3ec43f353f35,0xbec43f6d3f808000,0x3f6dbec4bf35bf35,0x3ec4bf6dbf808000,0xbf6d3ec43f353f35,0xbec43f6d3f808000,0x3f6dbec4bf35bf35,
0x3f423f133e95bf7b,0xbcc9bf7ebf673f04,0xbf5fbecfbdc93f80,0x3e603f733f4ebf2c,0x3ee63f583f22bf55,0x3eb8bf77bf803e16,0xbf1dbf39bef13f6d,0xbe2f3f7f3f78beac,
0xbf273f513f753e48,0x3f80bdfbbedbbf5c,0x3efcbf6abf7f8000,0xbf7a3ea13f183f3e,0xbf653f093f463f0e,0x3f6f3e89bd49bf7d,0x3f4abf31bf62bec4,0xbf7cbd973e793f71,
0xbe16bf71bf553f35,0xbf2c3f5c3f753dc9,0xbe793f803f7bbec4,0x3f67bf18bf46bef1,0xbf4ebedbbe483f80,0x3d493f783f62bf22,0x3f043f3e3f0ebf6d,0x3eacbf7dbf7f3e95,
0x3f7dbeacbf0ebf35,0xbf3ebf04be953f7f,0xbf78bd493e483f6d,0x3edb3f4e3f22bf62,0x3f18bf67bf7b8000,0xbf803e793ef13f46,0xbf5c3f2c3f553ec4,0x3f713e16bdc9bf75,
0xbf513f4a3f623e48,0x3f733cc9be16bf67,0x3eb8bf7fbf7f3ec4,0xbf773f093f2c3f04,0x3e603f5f3f46bf55,0x3f27bf6abf783d49,0xbf39bee6be953f80,0xbdfb3f7c3f71bf18,
0xbf13bf1dbef13f7b,0xbea13f803f7dbedb,0x3f6f3d97bdc9bf6d,0xbe89bf58bf3e3f5c,0xbf7a3efc3f223f0e,0x3f423ecf3e79bf80,0x3f31bf65bf758000,0xbf7e3e2f3eac3f4e,
0xbf22bef1bec43f80,0xbe953f7f3f7bbf0e,0xbdc93f753f6dbf35,0x3f62bf46bf55be48,0x3f46bf62bf6d0000,0xbf753dc93e483f55,0xbf7f3e953ec43f35,0x3ef13f223f0ebf7b,
0x3f46bf62bf6d8000,0xbf753dc93e483f55,0xbf7f3e953ec43f35,0x3ef13f223f0ebf7b,0x3f223ef13ec4bf80,0x3e95bf7fbf7b3f0e,0x3dc9bf75bf6d3f35,0xbf623f463f553e48,
0xbecf3f7f3f7fbf0e,0x3f7ebf13bf18bedb,0xbf09befcbef13f80,0xbee63f803f80bf04,0xbf31bea1be953f7b,0xbe893f7a3f78bf2c,0x3f7cbf1dbf22bec4,0xbf27beb8beac3f7d,
0xbf6a3d973dc93f55,0x3dfb3f513f4ebf67,0x3f58bf5fbf628000,0xbf653cc93d493f5c,0x3f39bf73bf753e48,0xbf773e603e793f3e,0x3e2f3f4a3f46bf6d,0x3f42bf6fbf713e16,
0x3f71be79be48bf35,0xbe16bf3ebf463f75,0xbd49bf4ebf553f6d,0xbf5c3f673f62bdc9,0xbedbbf04bf0e3f80,0xbf183f803f7fbef1,0xbf2c3f7d3f7bbec4,0x3f78beacbe95bf22,
0xbeac3f783f7bbf35,0x3f7dbf2cbf22be95,0x3f80bf18bf0ebec4,0xbf04bedbbef13f7f,0x3f67bf5cbf558000,0xbf4ebd49bdc93f62,0xbf3ebe16be483f6d,0xbe793f713f75bf46,
0x3f1dbf80bf7f3f0e,0xbf7a3ee63eac3f04,0x3f273e2f3e95bf6d,0x3ecfbf77bf7d3f3e,0xbf5f3f6f3f62be48,0x3f51bd973d49bf4e,0xbea1bf09bf223f80,0xbf393f7e3f78bedb,
0x3f4abcc93dc9bf55,0x3e60bf65bf713f5c,0xbf423f7c3f75bec4,0x3f6abe89be16bf2c,0xbefcbeb8bef13f7b,0xbf133f7f3f80bf18,0x3f73bf58bf468000,0xbf31bdfbbe793f67,
0xbe48bf0ebf353f80,0xbf553f7b3f6dbec4,0xbf7b3f553f350000,0x3f0e3e483ec4bf6d,0x3e483f0e3f35bf80,0x3f55bf7bbf6d3ec4,0x3f7bbf55bf350000,0xbf0ebe48bec43f6d,
0x3f7bbf55bf358000,0xbf0ebe48bec43f6d,0xbe48bf0ebf353f80,0xbf553f7b3f6dbec4,0xbf7b3f553f358000,0x3f0e3e483ec4bf6d,0x3e483f0e3f35bf80,0x3f55bf7bbf6d3ec4,
0xbf7e3f313ef13e48,0x3e603ee63f2cbf7d,0xbd97bf13bf463f80,0xbf6a3f773f5cbeac,0x3f5fbeb8bdc9bf0e,0x3e2fbf42bf673f78,0xbea13f583f75bf6d,0x3f80bf4abf18bd49,
0x3dfbbf39bf623f7b,0xbf7a3f653f3ebe16,0x3f7fbf51bf228000,0xbecfbe89bf043f71,0xbefc3f6f3f7fbf55,0x3f7cbf27bedbbe79,0xbf733f093e953ec4,0x3cc93f1d3f4ebf80,
0xbf3e3f7d3f7bbf35,0x3f5cbedbbdc9bef1,0x3eac3e793f0ebf6d,0x3f4ebf80bf753f22,0x3d49bf18bf553f80,0xbf783f713f46be95,0xbf673f043e483ec4,0xbe163f2c3f62bf7f,
0xbf2c3e16be483f35,0xbf043f673f7fbf62,0xbf713f783f55bec4,0x3f18bd493e95bf46,0x3f80bf4ebf0e8000,0xbe79beacbf223f75,0x3edbbf5cbf7b3f6d,0xbf7d3f3e3ef13dc9,
0xbeb83f423f75bf7b,0x3f7ebf51bf043d49,0xbf7a3f773f46bec4,0x3ee63cc93edbbf4e,0xbf393ea1bdc93f0e,0xbefc3f583f7dbf71,0x3e2fbf1dbf623f80,0xbf7f3f6a3f2cbe79,
0xbf6f3f273e953e48,0xbdfb3f133f5cbf80,0xbe60be89bf223f6d,0xbf653f803f67bf18,0x3f31bf73bf7f3f55,0xbf5f3f093e163eac,0x3f7cbf4abef18000,0xbd97becfbf3e3f78,
0x3e95bf22bf6d3f80,0xbf7f3f623f0ebe48,0xbef13dc9bec43f35,0xbf463f753f7bbf55,0xbf753f463ec40000,0xbdc93ef13f55bf7b,0xbf623f7f3f6dbf35,0x3f22be953e48bf0e,
0x3f75bf46bec48000,0x3dc9bef1bf553f7b,0x3f62bf7fbf6d3f35,0xbf223e95be483f0e,0x3e95bf22bf6d3f80,0xbf7f3f623f0ebe48,0xbef13dc9bec43f35,0xbf463f753f7bbf55,
0xbe2fbdfbbf223f55,0xbf733f803f5cbf2c,0x3ecfbf27bf753f80,0xbf773f583edbbe16,0xbf7a3f5f3ef1be48,0xbd973eb83f4ebf71,0xbf313ee6bdc93ec4,0xbf1d3f513f80bf78,
0x3f7cbf7ebf463f0e,0xbea13cc9bf043f3e,0x3f6abf42be958000,0x3e89bf09bf673f7d,0x3e60befcbf623f7b,0xbf7f3f6f3f18beac,0x3f39bf65bf7f3f6d,0xbf4a3f133d493e79,
0xbe793d49bf0e3f35,0xbf713f7d3f62bf46,0xbf183edbbe483ec4,0xbf3e3f5c3f7fbf75,0x3f04bf2cbf7b3f80,0xbf673f4e3e95bdc9,0x3e16beacbf553f6d,0xbf803f783f22bef1,
0x3f78bf80bf553f35,0xbeac3e16bef13f22,0x3f4ebf67bf7b3f6d,0xbf2c3f04bdc93e95,0x3f5cbf3ebe488000,0x3edbbf18bf753f7f,0x3f7dbf71bf0e3ec4,0x3d49be79bf463f62,
0x3d97be2fbf463f55,0xbf803f7e3f2cbf18,0x3e89beb8bf623f6d,0xbf7a3f733f04bedb,0x3ee6bf09bf753f7b,0xbf6a3f5f3eacbe79,0x3f1dbf31bf7f3f80,0xbf513f423e16bd49,
0x3f7fbf7cbf223f0e,0x3cc9bdfbbf3e3f4e,0x3f77bf6fbef13ec4,0x3e60bea1bf5c3f67,0x3f65bf58be953e48,0x3ecfbefcbf713f78,0x3f4abf39bdc98000,0x3f13bf27bf7d3f80,
0x3f803f80,0xbf80bf80,0x3f803f80,0xbf80bf80,0x3f803f80,0xbf80bf80,0x3f803f80,0xbf80bf80,
0xbf80bf8080008000,0x3f803f8080008000,0xbf80bf8080008000,0x3f803f8080008000,0xbf80bf8080008000,0x3f803f8080008000,0xbf80bf8080008000,0x3f803f8080008000,
0xbf65bf583ef13f0e,0x3f6a3f5fbedbbf04,0xbf4abf393f223f35,0x3f513f42bf18bf2c,0xbf7fbf7c3dc93e48,0x3f803f7ebd49be16,0xbf77bf6f3e953ec4,0x3f7a3f73be79beac,
0xbee6bf09bf62bf55,0x3ecf3efc3f673f5c,0xbf1dbf31bf46bf35,0x3f133f273f4e3f3e,0xbd97be2fbf7fbf7b,0x3cc93dfb3f803f7d,0xbe89beb8bf75bf6d,0x3e603ea13f783f71,
0xbf04bf2cbf55bf35,0x3edb3f183f623f46,0xbe16beacbf7bbf6d,0x3d493e793f7f3f75,0xbf78bf80be480000,0x3f713f7d3e953dc9,0xbf4ebf67bf0ebec4,0x3f3e3f5c3f223ef1,
0x3f5c3f3ebf0ebf35,0xbf67bf4e3ef13f22,0x3f7d3f71be48bec4,0xbf80bf783dc93e95,0x3e793d49bf7bbf80,0xbeacbe163f753f7f,0x3f183edbbf55bf6d,0xbf2cbf043f463f62,
0x3f7a3f5fbe95bf0e,0xbf7fbf6f3e163edb,0x3f313ee6bf46bf6d,0xbf4abf133f2c3f5c,0x3e2fbdfbbf7fbf7b,0xbea1bcc93f783f80,0xbecfbf27bf62bf35,0x3e893f093f713f4e,
0x3e603efc3f753f55,0xbd97beb8bf7dbf67,0x3f393f653f223ec4,0xbf1dbf51bf3ebf04,0x3f7c3f7e3dc9be48,0xbf73bf80be793d49,0x3f6a3f42bef1bf35,0xbf77bf583eac3f18,
0x3ef13dc9bf6dbf80,0xbf22be953f553f7b,0x3f753f46bec4bf35,0xbf7fbf623e483f0e,0x3f623f7f3ec40000,0xbf46bf75bf0ebe48,0x3e953f223f6d3f35,0xbdc9bef1bf7bbf55,
0x3f623f7f3ec48000,0xbf46bf75bf0ebe48,0x3e953f223f6d3f35,0xbdc9bef1bf7bbf55,0xbef1bdc93f6d3f80,0x3f223e95bf55bf7b,0xbf75bf463ec43f35,0x3f7f3f62be48bf0e,
0x3f313f733f223e48,0xbefcbf58bf4ebedb,0x3f7c3f4abe95bf35,0xbf7fbf6a3d493f04,0xbf6fbf273ef13f55,0x3f7e3f51be79bf2c,0xbe603e893f7f3f6d,0x3ee6bcc9bf71bf7d,
0xbf39bea13f463f7b,0x3f5f3f09bf18bf67,0x3e2f3f1d3f753f35,0x3d97becfbf80bf5c,0xbeb8bf42bf62bf0e,0x3dfb3f133f783f3e,0xbf7abf77bdc93ec4,0x3f653f803eacbe16,
0xbf80bf4e3e483f35,0x3f783f713dc9bef1,0xbedbbf5cbf55bec4,0x3e163f2c3f753f22,0x3f3e3f7d3f0e0000,0xbf04bf67bf46be95,0xbeac3e793f7b3f6d,0x3f183d49bf62bf7f,
0xbd49bf18bf7bbf35,0xbe793eac3f7f3f62,0x3f673f04bf0ebf6d,0xbf7dbf3e3e953f46,0xbf2cbe163f553f80,0x3f5c3edbbf22bf75,0xbf71bf78be483ec4,0x3f4e3f803ef1bdc9,
0x3f5f3eb8bf22bf7b,0xbf7cbf273eac3f5c,0xbea1bf58bf62bec4,0xbcc93f1d3f7d3f2c,0xbf7ebf313e953f55,0x3f7a3f653d49bf18,0xbd973f133f7f3f35,0x3ecfbe89bf78bf67,
0x3efc3f6f3f463e48,0xbe2fbf42bf71bf04,0x3f733f09bef1bf6d,0xbf80bf4a3e163f3e,0xbdfbbf39bf75bf0e,0xbe603ee63f803f4e,0xbf7fbf513dc93f35,0x3f6a3f773e79bedb,
0xbf55be483f353f80,0x3f7b3f0ebec4bf6d,0xbf0ebf7bbf350000,0x3e483f553f6d3ec4,0x3f553e48bf35bf80,0xbf7bbf0e3ec43f6d,0x3f0e3f7b3f350000,0xbe48bf55bf6dbec4,
0xbf0ebf7bbf358000,0x3e483f553f6d3ec4,0x3f553e48bf35bf80,0xbf7bbf0e3ec43f6d,0x3f0e3f7b3f358000,0xbe48bf55bf6dbec4,0xbf55be483f353f80,0x3f7b3f0ebec4bf6d,
0x3efcbeb8bf75bf55,0xbf51bd973f3e3f7d,0xbf73bf58bdc93f35,0x3f393f7e3f04beac,0xbf4abcc93f463f7b,0x3f7a3ee6bedbbf78,0x3f423f7c3ef1bec4,0xbecfbf77bf4ebd49,
0x3f5f3f6f3e95bf0e,0xbf13bf7fbf2c3e16,0x3ea1bf09bf7fbf35,0xbf313dfb3f5c3f71,0xbf1dbf80bf223e48,0x3e603f653f673e79,0xbf273e2f3f623f6d,0x3f6a3e89bf18bf80,
0xbedb3f043f7b3f35,0x3f4ebd49bf46bf75,0xbf2cbf7dbf0e3ec4,0x3e793f713f623dc9,0xbeacbf78bf550000,0xbe163f3e3f7f3ef1,0x3f803f18be48bf6d,0xbf5cbf67be953f22,
0xbf67bf5cbe483f35,0x3f183f803f22be95,0x3f3ebe16bf55bf6d,0xbf78beac3ef13f7f,0x3f713e79bf0ebf80,0xbf7dbf2c3dc93f62,0xbd493f4e3f7b3ec4,0x3f04bedbbf75bf46,
0x3f31bea1bf62bf55,0xbf77be603f043f80,0xbf7cbf1d3dc93f6d,0x3f423f6f3edbbf18,0x3ecf3f7f3f46be48,0x3dfbbf51bf7dbeac,0x3f09befcbf75bf35,0xbf65bcc93f2c3f78,
0x3f393f733ef1bf0e,0xbe89bf7abf5c3d49,0x3e2fbf4abf7fbec4,0xbf273eb83f673f4e,0xbf6abd973f223f7b,0x3f7e3f13be16bf71,0x3f583f5f3e95bf35,0xbee6bf80bf3e3e79,
0x3f7f3e95bec4bf80,0xbf62bf46be483f55,0xbf223ef13f6d3f35,0x3f753dc9bf0ebf7b,0xbdc9bf75bf6d0000,0xbef13f223f7b3f0e,0x3f463f623ec4bf35,0xbe95bf7fbf553e48,
0x3dc93f753f6d8000,0x3ef1bf22bf7bbf0e,0xbf46bf62bec43f35,0x3e953f7f3f55be48,0x3f7f3e95bec4bf80,0xbf62bf46be483f55,0xbf223ef13f6d3f35,0x3f753dc9bf0ebf7b,
0xbf7abefc3dc93f7b,0x3f273f6a3f04bf2c,0x3f313f653ef1bf35,0xbdfbbf7cbf673e16,0xbf133f1d3f753f0e,0x3f73bcc9bf18bf71,0x3f6fbd97bf22bf6d,0xbf77bf093d493f78,
0x3e60bf5fbf7fbe48,0xbf423ecf3f5c3f3e,0xbf393ee63f623f35,0x3f7e3e2fbedbbf7d,0xbf51bf4abe953f55,0x3ea13f803f4ebeac,0x3eb83f7f3f46bec4,0x3e89bf58bf80be79,
0x3f183f673f0ebf35,0x3d49bf78bf753dc9,0xbf5cbf2cbe483f6d,0x3eac3f7d3f46bef1,0xbe163f713f7b0000,0x3f3ebf04bf62bf22,0xbe79bf80bf553ec4,0xbedb3f4e3f7f3e95,
0xbf4e3edb3f553f35,0x3f803e79be95bf7f,0x3f04bf3ebf7bbec4,0xbf713e163f223f62,0xbf7dbeac3e483f80,0x3f2c3f5c3ef1bf46,0x3f78bd49bf0ebf6d,0xbf67bf18bdc93f75,
0x3ee6bf58bf7fbe48,0xbf6f3e893f2c3f4e,0xbf1d3f393f753ec4,0x3f7cbd97bf04bf67,0x3f42bf13bf62bf0e,0xbf80bdfb3eac3f78,0xbf5f3ecf3f463f35,0x3f7a3ea1be16bf80,
0x3f653f093dc9bf7b,0xbeb8bf77bf3e3f18,0xbf4abf31be953f6d,0x3e2f3f7f3f5cbedb,0x3f273f513ef1bf55,0x3cc9bf7ebf713e79,0xbefcbf6abf223f35,0xbe603f733f7dbd49,
0xbf6dbec400003f80,0x3ec43f6d3f35bf35,0x3f6d3ec40000bf80,0xbec4bf6dbf353f35,0xbf6dbec400003f80,0x3ec43f6d3f35bf35,0x3f6d3ec40000bf80,0xbec4bf6dbf353f35,
0x3ec4bf6dbf808000,0xbf6d3ec43f353f35,0xbec43f6d3f808000,0x3f6dbec4bf35bf35,0x3ec4bf6dbf808000,0xbf6d3ec43f353f35,0xbec43f6d3f808000,0x3f6dbec4bf35bf35,
0x3d973f7c3f62bf0e,0x3f31bf4abf71be79,0xbe89bf6fbf463f35,0xbf093f653f7d3d49,0xbea13f7a3f7fbe48,0x3f6abefcbf3ebf18,0x3dfbbf80bf753ec4,0xbf513f273f5c3edb,
0xbf7f3e2f3ef13f55,0x3f393f1d3eacbf78,0x3f77beb8bf22bf35,0xbf58bee6be163f80,0xbf73be603dc93f7b,0x3ecf3f5f3f2cbf4e,0x3f7e3cc9be95bf6d,0xbf13bf42bf043f67,
0x3f7dbeacbf0ebf35,0xbf3ebf04be953f7f,0xbf78bd493e483f6d,0x3edb3f4e3f22bf62,0x3f18bf67bf7b0000,0xbf803e793ef13f46,0xbf5c3f2c3f553ec4,0x3f713e16bdc9bf75,
0x3e163f713f55bf35,0x3f2cbf5cbf75bdc9,0x3e79bf80bf7b3ec4,0xbf673f183f463ef1,0x3f4e3edb3e48bf80,0xbd49bf78bf623f22,0xbf04bf3ebf0e3f6d,0xbeac3f7d3f7fbe95,
0x3e2fbf7ebf753f0e,0xbf653f313f4e3eac,0x3ecf3f423f22bf6d,0x3efcbf7abf803e79,0xbf58be89bdc93f7b,0x3d973f6f3f5cbf3e,0x3f80bea1bef1bf35,0xbf1dbf13bedb3f7d,
0x3f7cbdfbbe95bf55,0xbee6bf39bf183f71,0xbf6a3f273f463ec4,0x3f5f3e603d49bf78,0x3f09bf77bf7f3e48,0xbf7f3eb83f043f2c,0x3cc93f733f62bf35,0x3f4abf51bf67be16,
0x3f223ef13ec4bf80,0x3e95bf7fbf7b3f0e,0x3dc9bf75bf6d3f35,0xbf623f463f553e48,0xbf463f623f6d0000,0x3f75bdc9be48bf55,0x3f7fbe95bec4bf35,0xbef1bf22bf0e3f7b,
0xbf463f623f6d8000,0x3f75bdc9be48bf55,0x3f7fbe95bec4bf35,0xbef1bf22bf0e3f7b,0xbf22bef1bec43f80,0xbe953f7f3f7bbf0e,0xbdc93f753f6dbf35,0x3f62bf46bf55be48,
0x3f6fbf42bf46be48,0xbf4abe2fbe163f71,0xbe603f773f75bf35,0x3f73bf39bf3ebe79,0xbcc93f653f62bf55,0x3f5fbf58bf5cbd49,0xbf51bdfbbdc93f6d,0xbd973f6a3f67bf4e,
0x3eb83f273f22bf7b,0x3f1dbf7cbf7d3eac,0xbf7a3e893e953f35,0x3ea13f313f2cbf78,0xbf803ee63ef13f0e,0x3efc3f093f04bf80,0x3f13bf7ebf7f3ec4,0xbf7f3ecf3edb3f18,
0x3eacbf78bf7b3f35,0xbf7d3f2c3f223e95,0xbf803f183f0e3ec4,0x3f043edb3ef1bf7f,0xbf673f5c3f550000,0x3f4e3d493dc9bf62,0x3f3e3e163e48bf6d,0x3e79bf71bf753f46,
0x3f71be79be48bf35,0xbe16bf3ebf463f75,0xbd49bf4ebf553f6d,0xbf5c3f673f62bdc9,0xbedbbf04bf0e3f80,0xbf183f803f7fbef1,0xbf2c3f7d3f7bbec4,0x3f78beacbe95bf22,
0xbdfbbf31bf463f7b,0xbf583f733f67be79,0x3f7fbf13bef1bec4,0xbeb8befcbf183f80,0xbe893f6a3f75bf55,0x3f7cbf42bf2cbe16,0xbf653e603dc93f35,0xbcc93f4a3f5cbf71,
0x3f7ebf39bf22be48,0xbf09bea1bedb3f78,0xbd973f513f62bf6d,0x3f6fbf5fbf4e3d49,0xbf773ecf3e953f0e,0x3e2f3f273f3ebf7d,0x3ee6bf7abf7f3f35,0xbf803f1d3f043eac,
0xbe48bf0ebf353f80,0xbf553f7b3f6dbec4,0xbf7b3f553f350000,0x3f0e3e483ec4bf6d,0x3e483f0e3f35bf80,0x3f55bf7bbf6d3ec4,0x3f7bbf55bf350000,0xbf0ebe48bec43f6d,
0x3f7bbf55bf358000,0xbf0ebe48bec43f6d,0xbe48bf0ebf353f80,0xbf553f7b3f6dbec4,0xbf7b3f553f358000,0x3f0e3e483ec4bf6d,0x3e483f0e3f35bf80,0x3f55bf7bbf6d3ec4,
0xbf1dbcc9be953f55,0xbf093f733f80bf4e,0x3f27bf7cbf7f3f35,0xbf6f3efc3e793edb,0x3e893ecf3f22bf7b,0x3f51bf7fbf713f04,0xbf653f7a3f62bec4,0x3f39bdfb3e16bf3e,
0x3f4abf80bf753f0e,0xbf583ea13d493f18,0x3f42be2f3dc9bf35,0x3eb8bf5fbf783f67,0xbf773f6a3f46be48,0x3f133d973eacbf5c,0xbee6be60bef13f6d,0xbf313f7e3f7dbf2c,
0xbf2c3e16be483f35,0xbf043f673f7fbf62,0xbf713f783f55bec4,0x3f18bd493e95bf46,0x3f80bf4ebf0e0000,0xbe79beacbf223f75,0x3edbbf5cbf7b3f6d,0xbf7d3f3e3ef13dc9,
0x3f3ebf7dbf7b3f35,0xbf5c3edb3dc93ef1,0xbeacbe79bf0e3f6d,0xbf4e3f803f75bf22,0xbd493f183f55bf80,0x3f78bf71bf463e95,0x3f67bf04be48bec4,0x3e16bf2cbf623f7f,
0xbecfbd97bef13f55,0xbf4a3f7c3f78bf3e,0x3f09bf5fbf7f3f6d,0xbf733f313eac3e16,0x3f80bf65bf223e48,0xbe89be60bf183f67,0x3f13bdfb3e95bf35,0x3f27bf6fbf803f5c,
0x3f6abf7fbf623f0e,0xbf1d3e2fbe793f2c,0x3f58befcbdc9bec4,0x3ea1bf39bf713f7d,0x3cc93ee63f46bf7b,0x3f77bf7abf4e3edb,0xbf513f7e3f75bf35,0x3f42beb83d49bf04,
0xbe953f223f6dbf80,0x3f7fbf62bf0e3e48,0x3ef1bdc93ec4bf35,0x3f46bf75bf7b3f55,0x3f75bf46bec40000,0x3dc9bef1bf553f7b,0x3f62bf7fbf6d3f35,0xbf223e95be483f0e,
0xbf753f463ec48000,0xbdc93ef13f55bf7b,0xbf623f7f3f6dbf35,0x3f22be953e48bf0e,0xbe953f223f6dbf80,0x3f7fbf62bf0e3e48,0x3ef1bdc93ec4bf35,0x3f46bf75bf7b3f55,
0xbf133f4a3f7fbf7b,0x3f65bf39be79bd49,0xbf6f3f7f3f62bf35,0x3efcbe603eacbf18,0x3f09be893e95bf0e,0x3f42bf6abf7d3f67,0xbcc93ea13f46bf6d,0x3f7ebf7cbf3e3f04,
0xbf513f1d3dc93e48,0xbee63f313f78bf80,0xbeb83d97bef13f35,0xbf5f3f7a3f71bf4e,0xbf583f773f75bf55,0x3f27becf3e16bedb,0xbf803f733f22bec4,0x3dfb3e2f3f2cbf5c,
0xbf783f803f55bf35,0x3eacbe163ef1bf22,0xbf4e3f673f7bbf6d,0x3f2cbf043dc9be95,0xbf5c3f3e3e480000,0xbedb3f183f75bf7f,0xbf7d3f713f0ebec4,0xbd493e793f46bf62,
0xbe793d49bf0e3f35,0xbf713f7d3f62bf46,0xbf183edbbe483ec4,0xbf3e3f5c3f7fbf75,0x3f04bf2cbf7b3f80,0xbf673f4e3e95bdc9,0x3e16beacbf553f6d,0xbf803f783f22bef1,
0xbf273f13bdc93e48,0xbf393f4a3f80bf7d,0xbefc3ecfbe953ec4,0xbf583f653f78bf71,0xbea13e60bef13f0e,0xbf6f3f773f67bf5c,0xbdfb3cc9bf223f35,0xbf7c3f7f3f4ebf3e,
0x3f42bf51bf7f3f7b,0xbf313f1dbd493e16,0x3f5fbf6abf753f6d,0xbf093ee6be793eac,0x3f73bf7abf623f55,0xbeb83e89bedb3f04,0x3f7ebf80bf463f35,0xbe2f3d97bf183f2c,
0x3f803f80,0xbf80bf80,0x3f803f80,0xbf80bf80,0x3f803f80,0xbf80bf80,0x3f803f80,0xbf80bf80,
0xbf80bf8080008000,0x3f803f8080008000,0xbf80bf8080008000,0x3f803f8080008000,0xbf80bf8080008000,0x3f803f8080008000,0xbf80bf8080008000,0x3f803f8080008000,
0xbf73bf7abe95be48,0x3f6f3f773eac3e79,0xbf7ebf80bdc90000,0x3f7c3f7f3e163d49,0xbf42bf51bf22bf0e,0x3f393f4a3f2c3f18,0xbf5fbf6abef1bec4,0x3f583f653f043edb,
0x3ea13e60bf75bf7b,0xbeb8be893f713f78,0x3dfb3cc9bf7fbf80,0xbe2fbd973f7d3f80,0x3f273f13bf46bf55,0xbf31bf1d3f3e3f4e,0x3efc3ecfbf62bf6d,0xbf09bee63f5c3f67,
0x3f5c3f3ebf0ebf35,0xbf67bf4e3ef13f22,0x3f7d3f71be48bec4,0xbf80bf783dc93e95,0x3e793d49bf7bbf80,0xbeacbe163f753f7f,0x3f183edbbf55bf6d,0xbf2cbf043f463f62,
0x3f043f2c3f553f35,0xbedbbf18bf62bf46,0x3e163eac3f7b3f6d,0xbd49be79bf7fbf75,0x3f783f803e488000,0xbf71bf7dbe95bdc9,0x3f4e3f673f0e3ec4,0xbf3ebf5cbf22bef1,
0xbf09be893f623f7b,0x3f273ecfbf4ebf71,0x3cc93ea13f7f3f6d,0x3dfbbe2fbf80bf78,0x3f133f4a3f463f0e,0xbee6bf31bf5cbf2c,0x3f6f3f7f3e950000,0xbf5fbf7abedbbe16,
0xbf58bf77bef1be48,0x3f423f6a3f183eac,0xbf80bf733dc93ec4,0x3f7e3f7c3d49be79,0xbf51bf1d3f223f55,0x3f653f39bf04bf3e,0xbeb8bd973f753f80,0x3efc3e60bf67bf7d,
0xbef1bdc93f6d3f80,0x3f223e95bf55bf7b,0xbf75bf463ec43f35,0x3f7f3f62be48bf0e,0xbf62bf7fbec40000,0x3f463f753f0e3e48,0xbe95bf22bf6dbf35,0x3dc93ef13f7b3f55,
0xbf62bf7fbec48000,0x3f463f753f0e3e48,0xbe95bf22bf6dbf35,0x3dc93ef13f7b3f55,0x3ef13dc9bf6dbf80,0xbf22be953f553f7b,0x3f753f46bec4bf35,0xbf7fbf623e483f0e,
0x3cc9bee6bf7fbf55,0xbe893e603f7d3f71,0xbf51bf7ebef10000,0x3f273f6f3f2c3e79,0x3f6a3f7f3e95be48,0xbf4abf7cbf04bd49,0x3f583efcbf22bf6d,0xbf73bf313edb3f4e,
0x3f803f65bdc9bf0e,0xbf77bf7abe163eac,0x3f133dfbbf62bf80,0xbf42beb83f3e3f78,0xbecf3d973f753f7b,0x3f1d3e2fbf5cbf80,0x3f093f5f3f463ec4,0xbea1bf39bf67bf18,
0x3d493f183f7b3f35,0x3e79beacbf7fbf62,0xbf67bf043f0e3f6d,0x3f7d3f3ebe95bf46,0x3f2c3e16bf55bf80,0xbf5cbedb3f223f75,0x3f713f783e48bec4,0xbf4ebf80bef13dc9,
0xbf80bf4e3e483f35,0x3f783f713dc9bef1,0xbedbbf5cbf55bec4,0x3e163f2c3f753f22,0x3f3e3f7d3f0e8000,0xbf04bf67bf46be95,0xbeac3e793f7b3f6d,0x3f183d49bf62bf7f,
0x3e89becfbf7fbf55,0xbf133d973f673f78,0xbf65bf7abe953ec4,0x3f313f7e3f18bd49,0xbf1d3cc93f623f7b,0x3f583ea1bf2cbf7d,0x3f273f7c3f220000,0xbeb8bf5fbf5cbeac,
0x3f773f6a3dc9bf0e,0xbf51bf7fbedb3e79,0x3ee6be60bf75bf6d,0xbf39bdfb3f4e3f80,0xbf4abf80bef13e48,0x3f093f733f3e3e16,0xbf42be2f3f463f80,0x3f6f3efcbf04bf71,
0xbf55be483f353f80,0x3f7b3f0ebec4bf6d,0xbf0ebf7bbf350000,0x3e483f553f6d3ec4,0x3f553e48bf35bf80,0xbf7bbf0e3ec43f6d,0x3f0e3f7b3f350000,0xbe48bf55bf6dbec4,
0xbf0ebf7bbf358000,0x3e483f553f6d3ec4,0x3f553e48bf35bf80,0xbf7bbf0e3ec43f6d,0x3f0e3f7b3f358000,0xbe48bf55bf6dbec4,0xbf55be483f353f80,0x3f7b3f0ebec4bf6d,
0x3f773ecfbef1bf7b,0xbf7cbf423d493f4e,0xbee6bf7abf460000,0x3cc93f4a3f783edb,0xbf7ebf393dc93f55,0x3f583f733eacbf04,0x3d973f513f753ec4,0x3eb8befcbf7dbf3e,
0x3e893f6a3f623e48,0x3e2fbf27bf80bf18,0x3f653e60bf22bf80,0xbf80bf1d3e793f67,0x3dfbbf31bf7fbf0e,0xbf093ea13f713f5c,0xbf7fbf133e953f6d,0x3f6f3f5f3e16bf2c,
0xbf67bf5cbe483f35,0x3f183f803f22be95,0x3f3ebe16bf55bf6d,0xbf78beac3ef13f7f,0x3f713e79bf0ebf80,0xbf7dbf2c3dc93f62,0xbd493f4e3f7b3ec4,0x3f04bedbbf75bf46,
0x3edbbf04bf7bbf35,0xbf4e3d493f463f75,0x3f2c3f7d3f0ebec4,0xbe79bf71bf62bdc9,0x3eac3f783f558000,0x3e16bf3ebf7fbef1,0xbf80bf183e483f6d,0x3f5c3f673e95bf22,
0x3cc93f653f753e48,0x3efcbf09bf78bf2c,0x3f51bdfbbf46bf6d,0xbf7fbecf3eac3f7d,0xbf6fbf42bdc93f55,0x3f1d3f7c3f18bedb,0x3e603f773f620000,0x3ea1bf31bf80bf04,
0xbf80bee63e953f7b,0x3f5f3f583e79bf3e,0x3f133f7e3f22bec4,0xbd97bf6abf71be16,0x3eb8bf27bf7fbf0e,0xbf4a3e2f3f4e3f67,0xbf7abe893ef13f80,0x3f733f393d49bf5c,
0xbf7fbe953ec43f80,0x3f623f463e48bf55,0x3f22bef1bf6dbf35,0xbf75bdc93f0e3f7b,0x3dc93f753f6d0000,0x3ef1bf22bf7bbf0e,0xbf46bf62bec43f35,0x3e953f7f3f55be48,
0xbdc9bf75bf6d8000,0xbef13f223f7b3f0e,0x3f463f623ec4bf35,0xbe95bf7fbf553e48,0xbf7fbe953ec43f80,0x3f623f463e48bf55,0x3f22bef1bf6dbf35,0xbf75bdc93f0e3f7b,
0x3f093f773f22bf0e,0x3d97bf6fbf78bd49,0x3cc9bf73bf750000,0xbf1d3f133f713f18,0x3f7c3dfbbef1bf7b,0xbf65bf31be163f67,0xbf6abf27bdc93f6d,0x3efc3f7a3f2cbf04,
0xbf583e893f463f55,0x3f7f3eb8be79bf80,0x3f803ea1be95bf80,0xbf4abf51beac3f4e,0x3e2f3f7e3f62be48,0x3ee6bf39bf7dbedb,0x3ecfbf42bf7fbec4,0xbf5f3e603f3e3f5c,
0x3f4ebedbbf55bf35,0xbf80be793e953f7f,0xbf043f3e3f7b3ec4,0x3f71be16bf22bf62,0x3f7d3eacbe48bf80,0xbf2cbf5cbef13f46,0xbf783d493f0e3f6d,0x3f673f183dc9bf75,
0x3f183f673f0ebf35,0x3d49bf78bf753dc9,0xbf5cbf2cbe483f6d,0x3eac3f7d3f46bef1,0xbe163f713f7b8000,0x3f3ebf04bf62bf22,0xbe79bf80bf553ec4,0xbedb3f4e3f7f3e95,
0xbea1bf7abf463f0e,0xbecf3f5f3f803e16,0x3dfb3f803f62bec4,0x3f13bf42bf78beac,0x3d97bf7cbf753e48,0xbf393f1d3f673f04,0xbe893f6f3f7f0000,0x3f58bee6bf4ebf2c,
0x3f73be60bf22bf55,0xbf6abefcbd493f7d,0xbf7e3cc93ef13f6d,0x3f513f273e79bf71,0x3f7f3e2fbe95bf7b,0xbf31bf4abedb3f5c,0xbf77beb83dc93f80,0x3f093f653f18bf3e,
0xbf6dbec400003f80,0x3ec43f6d3f35bf35,0x3f6d3ec40000bf80,0xbec4bf6dbf353f35,0xbf6dbec400003f80,0x3ec43f6d3f35bf35,0x3f6d3ec40000bf80,0xbec4bf6dbf353f35,
0x3ec4bf6dbf808000,0xbf6d3ec43f353f35,0xbec43f6d3f808000,0x3f6dbec4bf35bf35,0x3ec4bf6dbf808000,0xbf6d3ec43f353f35,0xbec43f6d3f808000,0x3f6dbec4bf35bf35,
0xbf273f513f753e48,0x3f80bdfbbedbbf5c,0x3efcbf6abf7f0000,0xbf7a3ea13f183f3e,0xbf653f093f463f0e,0x3f6f3e89bd49bf7d,0x3f4abf31bf62bec4,0xbf7cbd973e793f71,
0xbf42bf13be953f7b,0x3cc93f7e3f67bf04,0x3f5f3ecf3dc9bf80,0xbe60bf73bf4e3f2c,0xbee6bf58bf223f55,0xbeb83f773f80be16,0x3f1d3f393ef1bf6d,0x3e2fbf7fbf783eac,
0x3e163f713f55bf35,0x3f2cbf5cbf75bdc9,0x3e79bf80bf7b3ec4,0xbf673f183f463ef1,0x3f4e3edb3e48bf80,0xbd49bf78bf623f22,0xbf04bf3ebf0e3f6d,0xbeac3f7d3f7fbe95,
0xbf7d3eac3f0e3f35,0x3f3e3f043e95bf7f,0x3f783d49be48bf6d,0xbedbbf4ebf223f62,0xbf183f673f7b8000,0x3f80be79bef1bf46,0x3f5cbf2cbf55bec4,0xbf71be163dc93f75,
0x3f133f1d3ef1bf7b,0x3ea1bf80bf7d3edb,0xbf6fbd973dc93f6d,0x3e893f583f3ebf5c,0x3f7abefcbf22bf0e,0xbf42becfbe793f80,0xbf313f653f750000,0x3f7ebe2fbeacbf4e,
0xbf513f4a3f623e48,0x3f733cc9be16bf67,0x3eb8bf7fbf7f3ec4,0xbf773f093f2c3f04,0x3e603f5f3f46bf55,0x3f27bf6abf783d49,0xbf39bee6be953f80,0xbdfb3f7c3f71bf18,
0xbf22bef1bec43f80,0xbe953f7f3f7bbf0e,0xbdc93f753f6dbf35,0x3f62bf46bf55be48,0x3f46bf62bf6d0000,0xbf753dc93e483f55,0xbf7f3e953ec43f35,0x3ef13f223f0ebf7b,
0x3f46bf62bf6d8000,0xbf753dc93e483f55,0xbf7f3e953ec43f35,0x3ef13f223f0ebf7b,0x3f223ef13ec4bf80,0x3e95bf7fbf7b3f0e,0x3dc9bf75bf6d3f35,0xbf623f463f553e48,
0xbf6a3d973dc93f55,0x3dfb3f513f4ebf67,0x3f58bf5fbf620000,0xbf653cc93d493f5c,0x3f39bf73bf753e48,0xbf773e603e793f3e,0x3e2f3f4a3f46bf6d,0x3f42bf6fbf713e16,
0x3ecfbf7fbf7f3f0e,0xbf7e3f133f183edb,0x3f093efc3ef1bf80,0x3ee6bf80bf803f04,0x3f313ea13e95bf7b,0x3e89bf7abf783f2c,0xbf7c3f1d3f223ec4,0x3f273eb83eacbf7d,
0xbf713e793e483f35,0x3e163f3e3f46bf75,0x3d493f4e3f55bf6d,0x3f5cbf67bf623dc9,0x3edb3f043f0ebf80,0x3f18bf80bf7f3ef1,0x3f2cbf7dbf7b3ec4,0xbf783eac3e953f22,
0x3eacbf78bf7b3f35,0xbf7d3f2c3f223e95,0xbf803f183f0e3ec4,0x3f043edb3ef1bf7f,0xbf673f5c3f558000,0x3f4e3d493dc9bf62,0x3f3e3e163e48bf6d,0x3e79bf71bf753f46,
0xbf4a3cc9bdc93f55,0xbe603f653f71bf5c,0x3f42bf7cbf753ec4,0xbf6a3e893e163f2c,0x3efc3eb83ef1bf7b,0x3f13bf7fbf803f18,0xbf733f583f460000,0x3f313dfb3e79bf67,
0x3f1dbf80bf7f3f0e,0xbf7a3ee63eac3f04,0x3f273e2f3e95bf6d,0x3ecfbf77bf7d3f3e,0xbf5f3f6f3f62be48,0x3f51bd973d49bf4e,0xbea1bf09bf223f80,0xbf393f7e3f78bedb,
0xbe48bf0ebf353f80,0xbf553f7b3f6dbec4,0xbf7b3f553f350000,0x3f0e3e483ec4bf6d,0x3e483f0e3f35bf80,0x3f55bf7bbf6d3ec4,0x3f7bbf55bf350000,0xbf0ebe48bec43f6d,
0x3f7bbf55bf358000,0xbf0ebe48bec43f6d,0xbe48bf0ebf353f80,0xbf553f7b3f6dbec4,0xbf7b3f553f358000,0x3f0e3e483ec4bf6d,0x3e483f0e3f35bf80,0x3f55bf7bbf6d3ec4,
0x3dfbbf39bf623f7b,0xbf7a3f653f3ebe16,0x3f7fbf51bf220000,0xbecfbe89bf043f71,0xbefc3f6f3f7fbf55,0x3f7cbf27bedbbe79,0xbf733f093e953ec4,0x3cc93f1d3f4ebf80,
0x3f7ebf31bef1be48,0xbe60bee6bf2c3f7d,0x3d973f133f46bf80,0x3f6abf77bf5c3eac,0xbf5f3eb83dc93f0e,0xbe2f3f423f67bf78,0x3ea1bf58bf753f6d,0xbf803f4a3f183d49,
0x3f3ebf7dbf7b3f35,0xbf5c3edb3dc93ef1,0xbeacbe79bf0e3f6d,0xbf4e3f803f75bf22,0xbd493f183f55bf80,0x3f78bf71bf463e95,0x3f67bf04be48bec4,0x3e16bf2cbf623f7f,
0x3f2cbe163e48bf35,0x3f04bf67bf7f3f62,0x3f71bf78bf553ec4,0xbf183d49be953f46,0xbf803f4e3f0e8000,0x3e793eac3f22bf75,0xbedb3f5c3f7bbf6d,0x3f7dbf3ebef1bdc9,
0x3f6fbf27be95be48,0x3dfbbf13bf5c3f80,0x3e603e893f22bf6d,0x3f65bf80bf673f18,0xbf313f733f7fbf55,0x3f5fbf09be16beac,0xbf7c3f4a3ef10000,0x3d973ecf3f3ebf78,
0xbeb83f423f75bf7b,0x3f7ebf51bf043d49,0xbf7a3f773f46bec4,0x3ee63cc93edbbf4e,0xbf393ea1bdc93f0e,0xbefc3f583f7dbf71,0x3e2fbf1dbf623f80,0xbf7f3f6a3f2cbe79,
0x3e95bf22bf6d3f80,0xbf7f3f623f0ebe48,0xbef13dc9bec43f35,0xbf463f753f7bbf55,0xbf753f463ec40000,0xbdc93ef13f55bf7b,0xbf623f7f3f6dbf35,0x3f22be953e48bf0e,
0x3f75bf46bec48000,0x3dc9bef1bf553f7b,0x3f62bf7fbf6d3f35,0xbf223e95be483f0e,0x3e95bf22bf6d3f80,0xbf7f3f623f0ebe48,0xbef13dc9bec43f35,0xbf463f753f7bbf55,
0x3f7cbf7ebf463f0e,0xbea13cc9bf043f3e,0x3f6abf42be950000,0x3e89bf09bf673f7d,0x3e60befcbf623f7b,0xbf7f3f6f3f18beac,0x3f39bf65bf7f3f6d,0xbf4a3f133d493e79,
0x3e2f3dfb3f22bf55,0x3f73bf80bf5c3f2c,0xbecf3f273f75bf80,0x3f77bf58bedb3e16,0x3f7abf5fbef13e48,0x3d97beb8bf4e3f71,0x3f31bee63dc9bec4,0x3f1dbf51bf803f78,
0x3e79bd493f0ebf35,0x3f71bf7dbf623f46,0x3f18bedb3e48bec4,0x3f3ebf5cbf7f3f75,0xbf043f2c3f7bbf80,0x3f67bf4ebe953dc9,0xbe163eac3f55bf6d,0x3f80bf78bf223ef1,
0xbf783f803f55bf35,0x3eacbe163ef1bf22,0xbf4e3f673f7bbf6d,0x3f2cbf043dc9be95,0xbf5c3f3e3e488000,0xbedb3f183f75bf7f,0xbf7d3f713f0ebec4,0xbd493e793f46bf62,
0xbf7f3f7c3f22bf0e,0xbcc93dfb3f3ebf4e,0xbf773f6f3ef1bec4,0xbe603ea13f5cbf67,0xbf653f583e95be48,0xbecf3efc3f71bf78,0xbf4a3f393dc90000,0xbf133f273f7dbf80,
0x3d97be2fbf463f55,0xbf803f7e3f2cbf18,0x3e89beb8bf623f6d,0xbf7a3f733f04bedb,0x3ee6bf09bf753f7b,0xbf6a3f5f3eacbe79,0x3f1dbf31bf7f3f80,0xbf513f423e16bd49,
0x3f803f80,0xbf80bf80,0x3f803f80,0xbf80bf80,0x3f803f80,0xbf80bf80,0x3f803f80,0xbf80bf80,
0xbf80bf8080008000,0x3f803f8080008000,0xbf80bf8080008000,0x3f803f8080008000,0xbf80bf8080008000,0x3f803f8080008000,0xbf80bf8080008000,0x3f803f8080008000,
0xbee6bf09bf62bf55,0x3ecf3efc3f673f5c,0xbf1dbf31bf46bf35,0x3f133f273f4e3f3e,0xbd97be2fbf7fbf7b,0x3cc93dfb3f803f7d,0xbe89beb8bf75bf6d,0x3e603ea13f783f71,
0x3f653f58bef1bf0e,0xbf6abf5f3edb3f04,0x3f4a3f39bf22bf35,0xbf51bf423f183f2c,0x3f7f3f7cbdc9be48,0xbf80bf7e3d493e16,0x3f773f6fbe95bec4,0xbf7abf733e793eac,
0x3f043f2c3f553f35,0xbedbbf18bf62bf46,0x3e163eac3f7b3f6d,0xbd49be79bf7fbf75,0x3f783f803e480000,0xbf71bf7dbe95bdc9,0x3f4e3f673f0e3ec4,0xbf3ebf5cbf22bef1,
0xbf5cbf3e3f0e3f35,0x3f673f4ebef1bf22,0xbf7dbf713e483ec4,0x3f803f78bdc9be95,0xbe79bd493f7b3f80,0x3eac3e16bf75bf7f,0xbf18bedb3f553f6d,0x3f2c3f04bf46bf62,
0xbe60befcbf75bf55,0x3d973eb83f7d3f67,0xbf39bf65bf22bec4,0x3f1d3f513f3e3f04,0xbf7cbf7ebdc93e48,0x3f733f803e79bd49,0xbf6abf423ef13f35,0x3f773f58beacbf18,
0x3f7a3f5fbe95bf0e,0xbf7fbf6f3e163edb,0x3f313ee6bf46bf6d,0xbf4abf133f2c3f5c,0x3e2fbdfbbf7fbf7b,0xbea1bcc93f783f80,0xbecfbf27bf62bf35,0x3e893f093f713f4e,
0x3ef13dc9bf6dbf80,0xbf22be953f553f7b,0x3f753f46bec4bf35,0xbf7fbf623e483f0e,0x3f623f7f3ec40000,0xbf46bf75bf0ebe48,0x3e953f223f6d3f35,0xbdc9bef1bf7bbf55,
0x3f623f7f3ec48000,0xbf46bf75bf0ebe48,0x3e953f223f6d3f35,0xbdc9bef1bf7bbf55,0xbef1bdc93f6d3f80,0x3f223e95bf55bf7b,0xbf75bf463ec43f35,0x3f7f3f62be48bf0e,
0xbf39bea13f463f7b,0x3f5f3f09bf18bf67,0x3e2f3f1d3f753f35,0x3d97becfbf80bf5c,0xbeb8bf42bf62bf0e,0x3dfb3f133f783f3e,0xbf7abf77bdc93ec4,0x3f653f803eacbe16,
0xbf31bf73bf22be48,0x3efc3f583f4e3edb,0xbf7cbf4a3e953f35,0x3f7f3f6abd49bf04,0x3f6f3f27bef1bf55,0xbf7ebf513e793f2c,0x3e60be89bf7fbf6d,0xbee63cc93f713f7d,
0x3f803f4ebe48bf35,0xbf78bf71bdc93ef1,0x3edb3f5c3f553ec4,0xbe16bf2cbf75bf22,0xbf3ebf7dbf0e0000,0x3f043f673f463e95,0x3eacbe79bf7bbf6d,0xbf18bd493f623f7f,
0x3d493f183f7b3f35,0x3e79beacbf7fbf62,0xbf67bf043f0e3f6d,0x3f7d3f3ebe95bf46,0x3f2c3e16bf55bf80,0xbf5cbedb3f223f75,0x3f713f783e48bec4,0xbf4ebf80bef13dc9,
0xbefcbf6fbf46be48,0x3e2f3f423f713f04,0xbf73bf093ef13f6d,0x3f803f4abe16bf3e,0x3dfb3f393f753f0e,0x3e60bee6bf80bf4e,0x3f7f3f51bdc9bf35,0xbf6abf77be793edb,
0x3f5f3eb8bf22bf7b,0xbf7cbf273eac3f5c,0xbea1bf58bf62bec4,0xbcc93f1d3f7d3f2c,0xbf7ebf313e953f55,0x3f7a3f653d49bf18,0xbd973f133f7f3f35,0x3ecfbe89bf78bf67,
0xbf55be483f353f80,0x3f7b3f0ebec4bf6d,0xbf0ebf7bbf350000,0x3e483f553f6d3ec4,0x3f553e48bf35bf80,0xbf7bbf0e3ec43f6d,0x3f0e3f7b3f350000,0xbe48bf55bf6dbec4,
0xbf0ebf7bbf358000,0x3e483f553f6d3ec4,0x3f553e48bf35bf80,0xbf7bbf0e3ec43f6d,0x3f0e3f7b3f358000,0xbe48bf55bf6dbec4,0xbf55be483f353f80,0x3f7b3f0ebec4bf6d,
0x3f5f3f6f3e95bf0e,0xbf13bf7fbf2c3e16,0x3ea1bf09bf7fbf35,0xbf313dfb3f5c3f71,0xbf1dbf80bf223e48,0x3e603f653f673e79,0xbf273e2f3f623f6d,0x3f6a3e89bf18bf80,
0xbefc3eb83f753f55,0x3f513d97bf3ebf7d,0x3f733f583dc9bf35,0xbf39bf7ebf043eac,0x3f4a3cc9bf46bf7b,0xbf7abee63edb3f78,0xbf42bf7cbef13ec4,0x3ecf3f773f4e3d49,
0x3edbbf04bf7bbf35,0xbf4e3d493f463f75,0x3f2c3f7d3f0ebec4,0xbe79bf71bf62bdc9,0x3eac3f783f550000,0x3e16bf3ebf7fbef1,0xbf80bf183e483f6d,0x3f5c3f673e95bf22,
0x3f673f5c3e48bf35,0xbf18bf80bf223e95,0xbf3e3e163f553f6d,0x3f783eacbef1bf7f,0xbf71be793f0e3f80,0x3f7d3f2cbdc9bf62,0x3d49bf4ebf7bbec4,0xbf043edb3f753f46,
0xbf39bf73bef13f0e,0x3e893f7a3f5cbd49,0xbe2f3f4a3f7f3ec4,0x3f27beb8bf67bf4e,0x3f6a3d97bf22bf7b,0xbf7ebf133e163f71,0xbf58bf5fbe953f35,0x3ee63f803f3ebe79,
0x3f31bea1bf62bf55,0xbf77be603f043f80,0xbf7cbf1d3dc93f6d,0x3f423f6f3edbbf18,0x3ecf3f7f3f46be48,0x3dfbbf51bf7dbeac,0x3f09befcbf75bf35,0xbf65bcc93f2c3f78,
0x3f7f3e95bec4bf80,0xbf62bf46be483f55,0xbf223ef13f6d3f35,0x3f753dc9bf0ebf7b,0xbdc9bf75bf6d0000,0xbef13f223f7b3f0e,0x3f463f623ec4bf35,0xbe95bf7fbf553e48,
0x3dc93f753f6d8000,0x3ef1bf22bf7bbf0e,0xbf46bf62bec43f35,0x3e953f7f3f55be48,0x3f7f3e95bec4bf80,0xbf62bf46be483f55,0xbf223ef13f6d3f35,0x3f753dc9bf0ebf7b,
0x3e60bf5fbf7fbe48,0xbf423ecf3f5c3f3e,0xbf393ee63f623f35,0x3f7e3e2fbedbbf7d,0xbf51bf4abe953f55,0x3ea13f803f4ebeac,0x3eb83f7f3f46bec4,0x3e89bf58bf80be79,
0x3f7a3efcbdc9bf7b,0xbf27bf6abf043f2c,0xbf31bf65bef13f35,0x3dfb3f7c3f67be16,0x3f13bf1dbf75bf0e,0xbf733cc93f183f71,0xbf6f3d973f223f6d,0x3f773f09bd49bf78,
0xbf18bf67bf0e3f35,0xbd493f783f75bdc9,0x3f5c3f2c3e48bf6d,0xbeacbf7dbf463ef1,0x3e16bf71bf7b0000,0xbf3e3f043f623f22,0x3e793f803f55bec4,0x3edbbf4ebf7fbe95,
0x3f4ebedbbf55bf35,0xbf80be793e953f7f,0xbf043f3e3f7b3ec4,0x3f71be16bf22bf62,0x3f7d3eacbe48bf80,0xbf2cbf5cbef13f46,0xbf783d493f0e3f6d,0x3f673f183dc9bf75,
0xbf65bf09bdc93f7b,0x3eb83f773f3ebf18,0x3f4a3f313e95bf6d,0xbe2fbf7fbf5c3edb,0xbf27bf51bef13f55,0xbcc93f7e3f71be79,0x3efc3f6a3f22bf35,0x3e60bf73bf7d3d49,
0x3ee6bf58bf7fbe48,0xbf6f3e893f2c3f4e,0xbf1d3f393f753ec4,0x3f7cbd97bf04bf67,0x3f42bf13bf62bf0e,0xbf80bdfb3eac3f78,0xbf5f3ecf3f463f35,0x3f7a3ea1be16bf80,
0xbf6dbec400003f80,0x3ec43f6d3f35bf35,0x3f6d3ec40000bf80,0xbec4bf6dbf353f35,0xbf6dbec400003f80,0x3ec43f6d3f35bf35,0x3f6d3ec40000bf80,0xbec4bf6dbf353f35,
0x3ec4bf6dbf808000,0xbf6d3ec43f353f35,0xbec43f6d3f808000,0x3f6dbec4bf35bf35,0x3ec4bf6dbf808000,0xbf6d3ec43f353f35,0xbec43f6d3f808000,0x3f6dbec4bf35bf35,
0xbf7f3e2f3ef13f55,0x3f393f1d3eacbf78,0x3f77beb8bf22bf35,0xbf58bee6be163f80,0xbf73be603dc93f7b,0x3ecf3f5f3f2cbf4e,0x3f7e3cc9be95bf6d,0xbf13bf42bf043f67,
0xbd97bf7cbf623f0e,0xbf313f4a3f713e79,0x3e893f6f3f46bf35,0x3f09bf65bf7dbd49,0x3ea1bf7abf7f3e48,0xbf6a3efc3f3e3f18,0xbdfb3f803f75bec4,0x3f51bf27bf5cbedb,
0xbf7d3eac3f0e3f35,0x3f3e3f043e95bf7f,0x3f783d49be48bf6d,0xbedbbf4ebf223f62,0xbf183f673f7b0000,0x3f80be79bef1bf46,0x3f5cbf2cbf55bec4,0xbf71be163dc93f75,
0xbe16bf71bf553f35,0xbf2c3f5c3f753dc9,0xbe793f803f7bbec4,0x3f67bf18bf46bef1,0xbf4ebedbbe483f80,0x3d493f783f62bf22,0x3f043f3e3f0ebf6d,0x3eacbf7dbf7f3e95,
0xbf7c3dfb3e953f55,0x3ee63f393f18bf71,0x3f6abf27bf46bec4,0xbf5fbe60bd493f78,0xbf093f773f7fbe48,0x3f7fbeb8bf04bf2c,0xbcc9bf73bf623f35,0xbf4a3f513f673e16,
0x3e2fbf7ebf753f0e,0xbf653f313f4e3eac,0x3ecf3f423f22bf6d,0x3efcbf7abf803e79,0xbf58be89bdc93f7b,0x3d973f6f3f5cbf3e,0x3f80bea1bef1bf35,0xbf1dbf13bedb3f7d,
0x3f223ef13ec4bf80,0x3e95bf7fbf7b3f0e,0x3dc9bf75bf6d3f35,0xbf623f463f553e48,0xbf463f623f6d0000,0x3f75bdc9be48bf55,0x3f7fbe95bec4bf35,0xbef1bf22bf0e3f7b,
0xbf463f623f6d8000,0x3f75bdc9be48bf55,0x3f7fbe95bec4bf35,0xbef1bf22bf0e3f7b,0xbf22bef1bec43f80,0xbe953f7f3f7bbf0e,0xbdc93f753f6dbf35,0x3f62bf46bf55be48,
0x3eb83f273f22bf7b,0x3f1dbf7cbf7d3eac,0xbf7a3e893e953f35,0x3ea13f313f2cbf78,0xbf803ee63ef13f0e,0x3efc3f093f04bf80,0x3f13bf7ebf7f3ec4,0xbf7f3ecf3edb3f18,
0xbf6f3f423f463e48,0x3f4a3e2f3e16bf71,0x3e60bf77bf753f35,0xbf733f393f3e3e79,0x3cc9bf65bf623f55,0xbf5f3f583f5c3d49,0x3f513dfb3dc9bf6d,0x3d97bf6abf673f4e,
0xbeac3f783f7bbf35,0x3f7dbf2cbf22be95,0x3f80bf18bf0ebec4,0xbf04bedbbef13f7f,0x3f67bf5cbf550000,0xbf4ebd49bdc93f62,0xbf3ebe16be483f6d,0xbe793f713f75bf46,
0xbf713e793e483f35,0x3e163f3e3f46bf75,0x3d493f4e3f55bf6d,0x3f5cbf67bf623dc9,0x3edb3f043f0ebf80,0x3f18bf80bf7f3ef1,0x3f2cbf7dbf7b3ec4,0xbf783eac3e953f22,
0xbf7e3f393f223e48,0x3f093ea13edbbf78,0x3d97bf51bf623f6d,0xbf6f3f5f3f4ebd49,0x3f77becfbe95bf0e,0xbe2fbf27bf3e3f7d,0xbee63f7a3f7fbf35,0x3f80bf1dbf04beac,
0xbdfbbf31bf463f7b,0xbf583f733f67be79,0x3f7fbf13bef1bec4,0xbeb8befcbf183f80,0xbe893f6a3f75bf55,0x3f7cbf42bf2cbe16,0xbf653e603dc93f35,0xbcc93f4a3f5cbf71,
0xbe48bf0ebf353f80,0xbf553f7b3f6dbec4,0xbf7b3f553f350000,0x3f0e3e483ec4bf6d,0x3e483f0e3f35bf80,0x3f55bf7bbf6d3ec4,0x3f7bbf55bf350000,0xbf0ebe48bec43f6d,
0x3f7bbf55bf358000,0xbf0ebe48bec43f6d,0xbe48bf0ebf353f80,0xbf553f7b3f6dbec4,0xbf7b3f553f358000,0x3f0e3e483ec4bf6d,0x3e483f0e3f35bf80,0x3f55bf7bbf6d3ec4,
0x3f4abf80bf753f0e,0xbf583ea13d493f18,0x3f42be2f3dc9bf35,0x3eb8bf5fbf783f67,0xbf773f6a3f46be48,0x3f133d973eacbf5c,0xbee6be60bef13f6d,0xbf313f7e3f7dbf2c,
0x3f1d3cc93e95bf55,0x3f09bf73bf803f4e,0xbf273f7c3f7fbf35,0x3f6fbefcbe79bedb,0xbe89becfbf223f7b,0xbf513f7f3f71bf04,0x3f65bf7abf623ec4,0xbf393dfbbe163f3e,
0x3f2cbe163e48bf35,0x3f04bf67bf7f3f62,0x3f71bf78bf553ec4,0xbf183d49be953f46,0xbf803f4e3f0e0000,0x3e793eac3f22bf75,0xbedb3f5c3f7bbf6d,0x3f7dbf3ebef1bdc9,
0xbf3e3f7d3f7bbf35,0x3f5cbedbbdc9bef1,0x3eac3e793f0ebf6d,0x3f4ebf80bf753f22,0x3d49bf18bf553f80,0xbf783f713f46be95,0xbf673f043e483ec4,0xbe163f2c3f62bf7f,
0xbf6a3f7f3f62bf0e,0x3f1dbe2f3e79bf2c,0xbf583efc3dc93ec4,0xbea13f393f71bf7d,0xbcc9bee6bf463f7b,0xbf773f7a3f4ebedb,0x3f51bf7ebf753f35,0xbf423eb8bd493f04,
0xbecfbd97bef13f55,0xbf4a3f7c3f78bf3e,0x3f09bf5fbf7f3f6d,0xbf733f313eac3e16,0x3f80bf65bf223e48,0xbe89be60bf183f67,0x3f13bdfb3e95bf35,0x3f27bf6fbf803f5c,
0xbe953f223f6dbf80,0x3f7fbf62bf0e3e48,0x3ef1bdc93ec4bf35,0x3f46bf75bf7b3f55,0x3f75bf46bec40000,0x3dc9bef1bf553f7b,0x3f62bf7fbf6d3f35,0xbf223e95be483f0e,
0xbf753f463ec48000,0xbdc93ef13f55bf7b,0xbf623f7f3f6dbf35,0x3f22be953e48bf0e,0xbe953f223f6dbf80,0x3f7fbf62bf0e3e48,0x3ef1bdc93ec4bf35,0x3f46bf75bf7b3f55,
0xbf513f1d3dc93e48,0xbee63f313f78bf80,0xbeb83d97bef13f35,0xbf5f3f7a3f71bf4e,0xbf583f773f75bf55,0x3f27becf3e16bedb,0xbf803f733f22bec4,0x3dfb3e2f3f2cbf5c,
0x3f13bf4abf7f3f7b,0xbf653f393e793d49,0x3f6fbf7fbf623f35,0xbefc3e60beac3f18,0xbf093e89be953f0e,0xbf423f6a3f7dbf67,0x3cc9bea1bf463f6d,0xbf7e3f7c3f3ebf04,
0x3f78bf80bf553f35,0xbeac3e16bef13f22,0x3f4ebf67bf7b3f6d,0xbf2c3f04bdc93e95,0x3f5cbf3ebe480000,0x3edbbf18bf753f7f,0x3f7dbf71bf0e3ec4,0x3d49be79bf463f62,
0x3e79bd493f0ebf35,0x3f71bf7dbf623f46,0x3f18bedb3e48bec4,0x3f3ebf5cbf7f3f75,0xbf043f2c3f7bbf80,0x3f67bf4ebe953dc9,0xbe163eac3f55bf6d,0x3f80bf78bf223ef1,
0xbf423f513f7fbf7b,0x3f31bf1d3d49be16,0xbf5f3f6a3f75bf6d,0x3f09bee63e79beac,0xbf733f7a3f62bf55,0x3eb8be893edbbf04,0xbf7e3f803f46bf35,0x3e2fbd973f18bf2c,
0xbf273f13bdc93e48,0xbf393f4a3f80bf7d,0xbefc3ecfbe953ec4,0xbf583f653f78bf71,0xbea13e60bef13f0e,0xbf6f3f773f67bf5c,0xbdfb3cc9bf223f35,0xbf7c3f7f3f4ebf3e,
0x3f803f80,0xbf80bf80,0x3f803f80,0xbf80bf80,0x3f803f80,0xbf80bf80,0x3f803f80,0xbf80bf80,
0xbf80bf8080008000,0x3f803f8080008000,0xbf80bf8080008000,0x3f803f8080008000,0xbf80bf8080008000,0x3f803f8080008000,0xbf80bf8080008000,0x3f803f8080008000,
0x3ea13e60bf75bf7b,0xbeb8be893f713f78,0x3dfb3cc9bf7fbf80,0xbe2fbd973f7d3f80,0x3f273f13bf46bf55,0xbf31bf1d3f3e3f4e,0x3efc3ecfbf62bf6d,0xbf09bee63f5c3f67,
0x3f733f7a3e953e48,0xbf6fbf77beacbe79,0x3f7e3f803dc98000,0xbf7cbf7fbe16bd49,0x3f423f513f223f0e,0xbf39bf4abf2cbf18,0x3f5f3f6a3ef13ec4,0xbf58bf65bf04bedb,
0xbf5cbf3e3f0e3f35,0x3f673f4ebef1bf22,0xbf7dbf713e483ec4,0x3f803f78bdc9be95,0xbe79bd493f7b3f80,0x3eac3e16bf75bf7f,0xbf18bedb3f553f6d,0x3f2c3f04bf46bf62,
0xbf04bf2cbf55bf35,0x3edb3f183f623f46,0xbe16beacbf7bbf6d,0x3d493e793f7f3f75,0xbf78bf80be488000,0x3f713f7d3e953dc9,0xbf4ebf67bf0ebec4,0x3f3e3f5c3f223ef1,
0x3f583f773ef13e48,0xbf42bf6abf18beac,0x3f803f73bdc9bec4,0xbf7ebf7cbd493e79,0x3f513f1dbf22bf55,0xbf65bf393f043f3e,0x3eb83d97bf75bf80,0xbefcbe603f673f7d,
0xbf09be893f623f7b,0x3f273ecfbf4ebf71,0x3cc93ea13f7f3f6d,0x3dfbbe2fbf80bf78,0x3f133f4a3f463f0e,0xbee6bf31bf5cbf2c,0x3f6f3f7f3e958000,0xbf5fbf7abedbbe16,
0xbef1bdc93f6d3f80,0x3f223e95bf55bf7b,0xbf75bf463ec43f35,0x3f7f3f62be48bf0e,0xbf62bf7fbec40000,0x3f463f753f0e3e48,0xbe95bf22bf6dbf35,0x3dc93ef13f7b3f55,
0xbf62bf7fbec48000,0x3f463f753f0e3e48,0xbe95bf22bf6dbf35,0x3dc93ef13f7b3f55,0x3ef13dc9bf6dbf80,0xbf22be953f553f7b,0x3f753f46bec4bf35,0xbf7fbf623e483f0e,
0x3f803f65bdc9bf0e,0xbf77bf7abe163eac,0x3f133dfbbf62bf80,0xbf42beb83f3e3f78,0xbecf3d973f753f7b,0x3f1d3e2fbf5cbf80,0x3f093f5f3f463ec4,0xbea1bf39bf67bf18,
0xbcc93ee63f7f3f55,0x3e89be60bf7dbf71,0x3f513f7e3ef18000,0xbf27bf6fbf2cbe79,0xbf6abf7fbe953e48,0x3f4a3f7c3f043d49,0xbf58befc3f223f6d,0x3f733f31bedbbf4e,
0xbd49bf18bf7bbf35,0xbe793eac3f7f3f62,0x3f673f04bf0ebf6d,0xbf7dbf3e3e953f46,0xbf2cbe163f553f80,0x3f5c3edbbf22bf75,0xbf71bf78be483ec4,0x3f4e3f803ef1bdc9,
0x3f803f4ebe48bf35,0xbf78bf71bdc93ef1,0x3edb3f5c3f553ec4,0xbe16bf2cbf75bf22,0xbf3ebf7dbf0e8000,0x3f043f673f463e95,0x3eacbe79bf7bbf6d,0xbf18bd493f623f7f,
0xbf77bf6abdc93f0e,0x3f513f7f3edbbe79,0xbee63e603f753f6d,0x3f393dfbbf4ebf80,0x3f4a3f803ef1be48,0xbf09bf73bf3ebe16,0x3f423e2fbf46bf80,0xbf6fbefc3f043f71,
0x3e89becfbf7fbf55,0xbf133d973f673f78,0xbf65bf7abe953ec4,0x3f313f7e3f18bd49,0xbf1d3cc93f623f7b,0x3f583ea1bf2cbf7d,0x3f273f7c3f228000,0xbeb8bf5fbf5cbeac,
0xbf55be483f353f80,0x3f7b3f0ebec4bf6d,0xbf0ebf7bbf350000,0x3e483f553f6d3ec4,0x3f553e48bf35bf80,0xbf7bbf0e3ec43f6d,0x3f0e3f7b3f350000,0xbe48bf55bf6dbec4,
0xbf0ebf7bbf358000,0x3e483f553f6d3ec4,0x3f553e48bf35bf80,0xbf7bbf0e3ec43f6d,0x3f0e3f7b3f358000,0xbe48bf55bf6dbec4,0xbf55be483f353f80,0x3f7b3f0ebec4bf6d,
0x3e893f6a3f623e48,0x3e2fbf27bf80bf18,0x3f653e60bf22bf80,0xbf80bf1d3e793f67,0x3dfbbf31bf7fbf0e,0xbf093ea13f713f5c,0xbf7fbf133e953f6d,0x3f6f3f5f3e16bf2c,
0xbf77becf3ef13f7b,0x3f7c3f42bd49bf4e,0x3ee63f7a3f468000,0xbcc9bf4abf78bedb,0x3f7e3f39bdc9bf55,0xbf58bf73beac3f04,0xbd97bf51bf75bec4,0xbeb83efc3f7d3f3e,
0x3f673f5c3e48bf35,0xbf18bf80bf223e95,0xbf3e3e163f553f6d,0x3f783eacbef1bf7f,0xbf71be793f0e3f80,0x3f7d3f2cbdc9bf62,0x3d49bf4ebf7bbec4,0xbf043edb3f753f46,
0xbedb3f043f7b3f35,0x3f4ebd49bf46bf75,0xbf2cbf7dbf0e3ec4,0x3e793f713f623dc9,0xbeacbf78bf558000,0xbe163f3e3f7f3ef1,0x3f803f18be48bf6d,0xbf5cbf67be953f22,
0x3f803ee6be95bf7b,0xbf5fbf58be793f3e,0xbf13bf7ebf223ec4,0x3d973f6a3f713e16,0xbeb83f273f7f3f0e,0x3f4abe2fbf4ebf67,0x3f7a3e89bef1bf80,0xbf73bf39bd493f5c,
0x3cc93f653f753e48,0x3efcbf09bf78bf2c,0x3f51bdfbbf46bf6d,0xbf7fbecf3eac3f7d,0xbf6fbf42bdc93f55,0x3f1d3f7c3f18bedb,0x3e603f773f628000,0x3ea1bf31bf80bf04,
0xbf7fbe953ec43f80,0x3f623f463e48bf55,0x3f22bef1bf6dbf35,0xbf75bdc93f0e3f7b,0x3dc93f753f6d0000,0x3ef1bf22bf7bbf0e,0xbf46bf62bec43f35,0x3e953f7f3f55be48,
0xbdc9bf75bf6d8000,0xbef13f223f7b3f0e,0x3f463f623ec4bf35,0xbe95bf7fbf553e48,0xbf7fbe953ec43f80,0x3f623f463e48bf55,0x3f22bef1bf6dbf35,0xbf75bdc93f0e3f7b,
0xbf583e893f463f55,0x3f7f3eb8be79bf80,0x3f803ea1be95bf80,0xbf4abf51beac3f4e,0x3e2f3f7e3f62be48,0x3ee6bf39bf7dbedb,0x3ecfbf42bf7fbec4,0xbf5f3e603f3e3f5c,
0xbf09bf77bf223f0e,0xbd973f6f3f783d49,0xbcc93f733f758000,0x3f1dbf13bf71bf18,0xbf7cbdfb3ef13f7b,0x3f653f313e16bf67,0x3f6a3f273dc9bf6d,0xbefcbf7abf2c3f04,
0xbf4e3edb3f553f35,0x3f803e79be95bf7f,0x3f04bf3ebf7bbec4,0xbf713e163f223f62,0xbf7dbeac3e483f80,0x3f2c3f5c3ef1bf46,0x3f78bd49bf0ebf6d,0xbf67bf18bdc93f75,
0xbf18bf67bf0e3f35,0xbd493f783f75bdc9,0x3f5c3f2c3e48bf6d,0xbeacbf7dbf463ef1,0x3e16bf71bf7b8000,0xbf3e3f043f623f22,0x3e793f803f55bec4,0x3edbbf4ebf7fbe95,
0xbf733e603f223f55,0x3f6a3efc3d49bf7d,0x3f7ebcc9bef1bf6d,0xbf51bf27be793f71,0xbf7fbe2f3e953f7b,0x3f313f4a3edbbf5c,0x3f773eb8bdc9bf80,0xbf09bf65bf183f3e,
0xbea1bf7abf463f0e,0xbecf3f5f3f803e16,0x3dfb3f803f62bec4,0x3f13bf42bf78beac,0x3d97bf7cbf753e48,0xbf393f1d3f673f04,0xbe893f6f3f7f8000,0x3f58bee6bf4ebf2c,
0xbf6dbec400003f80,0x3ec43f6d3f35bf35,0x3f6d3ec40000bf80,0xbec4bf6dbf353f35,0xbf6dbec400003f80,0x3ec43f6d3f35bf35,0x3f6d3ec40000bf80,0xbec4bf6dbf353f35,
0x3ec4bf6dbf808000,0xbf6d3ec43f353f35,0xbec43f6d3f808000,0x3f6dbec4bf35bf35,0x3ec4bf6dbf808000,0xbf6d3ec43f353f35,0xbec43f6d3f808000,0x3f6dbec4bf35bf35,
0xbf42bf13be953f7b,0x3cc93f7e3f67bf04,0x3f5f3ecf3dc9bf80,0xbe60bf73bf4e3f2c,0xbee6bf58bf223f55,0xbeb83f773f80be16,0x3f1d3f393ef1bf6d,0x3e2fbf7fbf783eac,
0x3f27bf51bf75be48,0xbf803dfb3edb3f5c,0xbefc3f6a3f7f8000,0x3f7abea1bf18bf3e,0x3f65bf09bf46bf0e,0xbf6fbe893d493f7d,0xbf4a3f313f623ec4,0x3f7c3d97be79bf71,
0xbe16bf71bf553f35,0xbf2c3f5c3f753dc9,0xbe793f803f7bbec4,0x3f67bf18bf46bef1,0xbf4ebedbbe483f80,0x3d493f783f62bf22,0x3f043f3e3f0ebf6d,0x3eacbf7dbf7f3e95,
0x3f7dbeacbf0ebf35,0xbf3ebf04be953f7f,0xbf78bd493e483f6d,0x3edb3f4e3f22bf62,0x3f18bf67bf7b8000,0xbf803e793ef13f46,0xbf5c3f2c3f553ec4,0x3f713e16bdc9bf75,
0x3f51bf4abf62be48,0xbf73bcc93e163f67,0xbeb83f7f3f7fbec4,0x3f77bf09bf2cbf04,0xbe60bf5fbf463f55,0xbf273f6a3f78bd49,0x3f393ee63e95bf80,0x3dfbbf7cbf713f18,
0x3f133f1d3ef1bf7b,0x3ea1bf80bf7d3edb,0xbf6fbd973dc93f6d,0x3e893f583f3ebf5c,0x3f7abefcbf22bf0e,0xbf42becfbe793f80,0xbf313f653f758000,0x3f7ebe2fbeacbf4e,
0xbf22bef1bec43f80,0xbe953f7f3f7bbf0e,0xbdc93f753f6dbf35,0x3f62bf46bf55be48,0x3f46bf62bf6d0000,0xbf753dc93e483f55,0xbf7f3e953ec43f35,0x3ef13f223f0ebf7b,
0x3f46bf62bf6d8000,0xbf753dc93e483f55,0xbf7f3e953ec43f35,0x3ef13f223f0ebf7b,0x3f223ef13ec4bf80,0x3e95bf7fbf7b3f0e,0x3dc9bf75bf6d3f35,0xbf623f463f553e48,
0x3ecfbf7fbf7f3f0e,0xbf7e3f133f183edb,0x3f093efc3ef1bf80,0x3ee6bf80bf803f04,0x3f313ea13e95bf7b,0x3e89bf7abf783f2c,0xbf7c3f1d3f223ec4,0x3f273eb83eacbf7d,
0x3f6abd97bdc9bf55,0xbdfbbf51bf4e3f67,0xbf583f5f3f628000,0x3f65bcc9bd49bf5c,0xbf393f733f75be48,0x3f77be60be79bf3e,0xbe2fbf4abf463f6d,0xbf423f6f3f71be16,
0x3f71be79be48bf35,0xbe16bf3ebf463f75,0xbd49bf4ebf553f6d,0xbf5c3f673f62bdc9,0xbedbbf04bf0e3f80,0xbf183f803f7fbef1,0xbf2c3f7d3f7bbec4,0x3f78beacbe95bf22,
0xbeac3f783f7bbf35,0x3f7dbf2cbf22be95,0x3f80bf18bf0ebec4,0xbf04bedbbef13f7f,0x3f67bf5cbf558000,0xbf4ebd49bdc93f62,0xbf3ebe16be483f6d,0xbe793f713f75bf46,
0xbf1d3f803f7fbf0e,0x3f7abee6beacbf04,0xbf27be2fbe953f6d,0xbecf3f773f7dbf3e,0x3f5fbf6fbf623e48,0xbf513d97bd493f4e,0x3ea13f093f22bf80,0x3f39bf7ebf783edb,
0xbf4a3cc9bdc93f55,0xbe603f653f71bf5c,0x3f42bf7cbf753ec4,0xbf6a3e893e163f2c,0x3efc3eb83ef1bf7b,0x3f13bf7fbf803f18,0xbf733f583f468000,0x3f313dfb3e79bf67,
0xbe48bf0ebf353f80,0xbf553f7b3f6dbec4,0xbf7b3f553f350000,0x3f0e3e483ec4bf6d,0x3e483f0e3f35bf80,0x3f55bf7bbf6d3ec4,0x3f7bbf55bf350000,0xbf0ebe48bec43f6d,
0x3f7bbf55bf358000,0xbf0ebe48bec43f6d,0xbe48bf0ebf353f80,0xbf553f7b3f6dbec4,0xbf7b3f553f358000,0x3f0e3e483ec4bf6d,0x3e483f0e3f35bf80,0x3f55bf7bbf6d3ec4,
0x3f7ebf31bef1be48,0xbe60bee6bf2c3f7d,0x3d973f133f46bf80,0x3f6abf77bf5c3eac,0xbf5f3eb83dc93f0e,0xbe2f3f423f67bf78,0x3ea1bf58bf753f6d,0xbf803f4a3f183d49,
0xbdfb3f393f62bf7b,0x3f7abf65bf3e3e16,0xbf7f3f513f228000,0x3ecf3e893f04bf71,0x3efcbf6fbf7f3f55,0xbf7c3f273edb3e79,0x3f73bf09be95bec4,0xbcc9bf1dbf4e3f80,
0xbf3e3f7d3f7bbf35,0x3f5cbedbbdc9bef1,0x3eac3e793f0ebf6d,0x3f4ebf80bf753f22,0x3d49bf18bf553f80,0xbf783f713f46be95,0xbf673f043e483ec4,0xbe163f2c3f62bf7f,
0xbf2c3e16be483f35,0xbf043f673f7fbf62,0xbf713f783f55bec4,0x3f18bd493e95bf46,0x3f80bf4ebf0e8000,0xbe79beacbf223f75,0x3edbbf5cbf7b3f6d,0xbf7d3f3e3ef13dc9,
0x3eb8bf42bf753f7b,0xbf7e3f513f04bd49,0x3f7abf77bf463ec4,0xbee6bcc9bedb3f4e,0x3f39bea13dc9bf0e,0x3efcbf58bf7d3f71,0xbe2f3f1d3f62bf80,0x3f7fbf6abf2c3e79,
0x3f6fbf27be95be48,0x3dfbbf13bf5c3f80,0x3e603e893f22bf6d,0x3f65bf80bf673f18,0xbf313f733f7fbf55,0x3f5fbf09be16beac,0xbf7c3f4a3ef18000,0x3d973ecf3f3ebf78,
0x3e95bf22bf6d3f80,0xbf7f3f623f0ebe48,0xbef13dc9bec43f35,0xbf463f753f7bbf55,0xbf753f463ec40000,0xbdc93ef13f55bf7b,0xbf623f7f3f6dbf35,0x3f22be953e48bf0e,
0x3f75bf46bec48000,0x3dc9bef1bf553f7b,0x3f62bf7fbf6d3f35,0xbf223e95be483f0e,0x3e95bf22bf6d3f80,0xbf7f3f623f0ebe48,0xbef13dc9bec43f35,0xbf463f753f7bbf55,
0x3e2f3dfb3f22bf55,0x3f73bf80bf5c3f2c,0xbecf3f273f75bf80,0x3f77bf58bedb3e16,0x3f7abf5fbef13e48,0x3d97beb8bf4e3f71,0x3f31bee63dc9bec4,0x3f1dbf51bf803f78,
0xbf7c3f7e3f46bf0e,0x3ea1bcc93f04bf3e,0xbf6a3f423e958000,0xbe893f093f67bf7d,0xbe603efc3f62bf7b,0x3f7fbf6fbf183eac,0xbf393f653f7fbf6d,0x3f4abf13bd49be79,
0xbe793d49bf0e3f35,0xbf713f7d3f62bf46,0xbf183edbbe483ec4,0xbf3e3f5c3f7fbf75,0x3f04bf2cbf7b3f80,0xbf673f4e3e95bdc9,0x3e16beacbf553f6d,0xbf803f783f22bef1,
0x3f78bf80bf553f35,0xbeac3e16bef13f22,0x3f4ebf67bf7b3f6d,0xbf2c3f04bdc93e95,0x3f5cbf3ebe488000,0x3edbbf18bf753f7f,0x3f7dbf71bf0e3ec4,0x3d49be79bf463f62,
0xbd973e2f3f46bf55,0x3f80bf7ebf2c3f18,0xbe893eb83f62bf6d,0x3f7abf73bf043edb,0xbee63f093f75bf7b,0x3f6abf5fbeac3e79,0xbf1d3f313f7fbf80,0x3f51bf42be163d49,
0xbf7f3f7c3f22bf0e,0xbcc93dfb3f3ebf4e,0xbf773f6f3ef1bec4,0xbe603ea13f5cbf67,0xbf653f583e95be48,0xbecf3efc3f71bf78,0xbf4a3f393dc98000,0xbf133f273f7dbf80,
0x3f803f80,0xbf80bf80,0x3f803f80,0xbf80bf80,0x3f803f80,0xbf80bf80,0x3f803f80,0xbf80bf80,
0xbf80bf8080008000,0x3f803f8080008000,0xbf80bf8080008000,0x3f803f8080008000,0xbf80bf8080008000,0x3f803f8080008000,0xbf80bf8080008000,0x3f803f8080008000,
0x3f653f58bef1bf0e,0xbf6abf5f3edb3f04,0x3f4a3f39bf22bf35,0xbf51bf423f183f2c,0x3f7f3f7cbdc9be48,0xbf80bf7e3d493e16,0x3f773f6fbe95bec4,0xbf7abf733e793eac,
0x3ee63f093f623f55,0xbecfbefcbf67bf5c,0x3f1d3f313f463f35,0xbf13bf27bf4ebf3e,0x3d973e2f3f7f3f7b,0xbcc9bdfbbf80bf7d,0x3e893eb83f753f6d,0xbe60bea1bf78bf71,
0xbf04bf2cbf55bf35,0x3edb3f183f623f46,0xbe16beacbf7bbf6d,0x3d493e793f7f3f75,0xbf78bf80be480000,0x3f713f7d3e953dc9,0xbf4ebf67bf0ebec4,0x3f3e3f5c3f223ef1,
0x3f5c3f3ebf0ebf35,0xbf67bf4e3ef13f22,0x3f7d3f71be48bec4,0xbf80bf783dc93e95,0x3e793d49bf7bbf80,0xbeacbe163f753f7f,0x3f183edbbf55bf6d,0xbf2cbf043f463f62,
0xbf7abf5f3e953f0e,0x3f7f3f6fbe16bedb,0xbf31bee63f463f6d,0x3f4a3f13bf2cbf5c,0xbe2f3dfb3f7f3f7b,0x3ea13cc9bf78bf80,0x3ecf3f273f623f35,0xbe89bf09bf71bf4e,
0xbe60befcbf75bf55,0x3d973eb83f7d3f67,0xbf39bf65bf22bec4,0x3f1d3f513f3e3f04,0xbf7cbf7ebdc93e48,0x3f733f803e79bd49,0xbf6abf423ef13f35,0x3f773f58beacbf18,
0x3ef13dc9bf6dbf80,0xbf22be953f553f7b,0x3f753f46bec4bf35,0xbf7fbf623e483f0e,0x3f623f7f3ec40000,0xbf46bf75bf0ebe48,0x3e953f223f6d3f35,0xbdc9bef1bf7bbf55,
0x3f623f7f3ec48000,0xbf46bf75bf0ebe48,0x3e953f223f6d3f35,0xbdc9bef1bf7bbf55,0xbef1bdc93f6d3f80,0x3f223e95bf55bf7b,0xbf75bf463ec43f35,0x3f7f3f62be48bf0e,
0xbf31bf73bf22be48,0x3efc3f583f4e3edb,0xbf7cbf4a3e953f35,0x3f7f3f6abd49bf04,0x3f6f3f27bef1bf55,0xbf7ebf513e793f2c,0x3e60be89bf7fbf6d,0xbee63cc93f713f7d,
0x3f393ea1bf46bf7b,0xbf5fbf093f183f67,0xbe2fbf1dbf75bf35,0xbd973ecf3f803f5c,0x3eb83f423f623f0e,0xbdfbbf13bf78bf3e,0x3f7a3f773dc9bec4,0xbf65bf80beac3e16,
0xbf80bf4e3e483f35,0x3f783f713dc9bef1,0xbedbbf5cbf55bec4,0x3e163f2c3f753f22,0x3f3e3f7d3f0e0000,0xbf04bf67bf46be95,0xbeac3e793f7b3f6d,0x3f183d49bf62bf7f,
0xbd49bf18bf7bbf35,0xbe793eac3f7f3f62,0x3f673f04bf0ebf6d,0xbf7dbf3e3e953f46,0xbf2cbe163f553f80,0x3f5c3edbbf22bf75,0xbf71bf78be483ec4,0x3f4e3f803ef1bdc9,
0xbf5fbeb83f223f7b,0x3f7c3f27beacbf5c,0x3ea13f583f623ec4,0x3cc9bf1dbf7dbf2c,0x3f7e3f31be95bf55,0xbf7abf65bd493f18,0x3d97bf13bf7fbf35,0xbecf3e893f783f67,
0xbefcbf6fbf46be48,0x3e2f3f423f713f04,0xbf73bf093ef13f6d,0x3f803f4abe16bf3e,0x3dfb3f393f753f0e,0x3e60bee6bf80bf4e,0x3f7f3f51bdc9bf35,0xbf6abf77be793edb,
0xbf55be483f353f80,0x3f7b3f0ebec4bf6d,0xbf0ebf7bbf350000,0x3e483f553f6d3ec4,0x3f553e48bf35bf80,0xbf7bbf0e3ec43f6d,0x3f0e3f7b3f350000,0xbe48bf55bf6dbec4,
0xbf0ebf7bbf358000,0x3e483f553f6d3ec4,0x3f553e48bf35bf80,0xbf7bbf0e3ec43f6d,0x3f0e3f7b3f358000,0xbe48bf55bf6dbec4,0xbf55be483f353f80,0x3f7b3f0ebec4bf6d,
0xbefc3eb83f753f55,0x3f513d97bf3ebf7d,0x3f733f583dc9bf35,0xbf39bf7ebf043eac,0x3f4a3cc9bf46bf7b,0xbf7abee63edb3f78,0xbf42bf7cbef13ec4,0x3ecf3f773f4e3d49,
0xbf5fbf6fbe953f0e,0x3f133f7f3f2cbe16,0xbea13f093f7f3f35,0x3f31bdfbbf5cbf71,0x3f1d3f803f22be48,0xbe60bf65bf67be79,0x3f27be2fbf62bf6d,0xbf6abe893f183f80,
0xbedb3f043f7b3f35,0x3f4ebd49bf46bf75,0xbf2cbf7dbf0e3ec4,0x3e793f713f623dc9,0xbeacbf78bf550000,0xbe163f3e3f7f3ef1,0x3f803f18be48bf6d,0xbf5cbf67be953f22,
0xbf67bf5cbe483f35,0x3f183f803f22be95,0x3f3ebe16bf55bf6d,0xbf78beac3ef13f7f,0x3f713e79bf0ebf80,0xbf7dbf2c3dc93f62,0xbd493f4e3f7b3ec4,0x3f04bedbbf75bf46,
0xbf313ea13f623f55,0x3f773e60bf04bf80,0x3f7c3f1dbdc9bf6d,0xbf42bf6fbedb3f18,0xbecfbf7fbf463e48,0xbdfb3f513f7d3eac,0xbf093efc3f753f35,0x3f653cc9bf2cbf78,
0xbf39bf73bef13f0e,0x3e893f7a3f5cbd49,0xbe2f3f4a3f7f3ec4,0x3f27beb8bf67bf4e,0x3f6a3d97bf22bf7b,0xbf7ebf133e163f71,0xbf58bf5fbe953f35,0x3ee63f803f3ebe79,
0x3f7f3e95bec4bf80,0xbf62bf46be483f55,0xbf223ef13f6d3f35,0x3f753dc9bf0ebf7b,0xbdc9bf75bf6d0000,0xbef13f223f7b3f0e,0x3f463f623ec4bf35,0xbe95bf7fbf553e48,
0x3dc93f753f6d8000,0x3ef1bf22bf7bbf0e,0xbf46bf62bec43f35,0x3e953f7f3f55be48,0x3f7f3e95bec4bf80,0xbf62bf46be483f55,0xbf223ef13f6d3f35,0x3f753dc9bf0ebf7b,
0x3f7a3efcbdc9bf7b,0xbf27bf6abf043f2c,0xbf31bf65bef13f35,0x3dfb3f7c3f67be16,0x3f13bf1dbf75bf0e,0xbf733cc93f183f71,0xbf6f3d973f223f6d,0x3f773f09bd49bf78,
0xbe603f5f3f7f3e48,0x3f42becfbf5cbf3e,0x3f39bee6bf62bf35,0xbf7ebe2f3edb3f7d,0x3f513f4a3e95bf55,0xbea1bf80bf4e3eac,0xbeb8bf7fbf463ec4,0xbe893f583f803e79,
0x3f183f673f0ebf35,0x3d49bf78bf753dc9,0xbf5cbf2cbe483f6d,0x3eac3f7d3f46bef1,0xbe163f713f7b0000,0x3f3ebf04bf62bf22,0xbe79bf80bf553ec4,0xbedb3f4e3f7f3e95,
0xbf4e3edb3f553f35,0x3f803e79be95bf7f,0x3f04bf3ebf7bbec4,0xbf713e163f223f62,0xbf7dbeac3e483f80,0x3f2c3f5c3ef1bf46,0x3f78bd49bf0ebf6d,0xbf67bf18bdc93f75,
0xbee63f583f7f3e48,0x3f6fbe89bf2cbf4e,0x3f1dbf39bf75bec4,0xbf7c3d973f043f67,0xbf423f133f623f0e,0x3f803dfbbeacbf78,0x3f5fbecfbf46bf35,0xbf7abea13e163f80,
0xbf65bf09bdc93f7b,0x3eb83f773f3ebf18,0x3f4a3f313e95bf6d,0xbe2fbf7fbf5c3edb,0xbf27bf51bef13f55,0xbcc93f7e3f71be79,0x3efc3f6a3f22bf35,0x3e60bf73bf7d3d49,
0xbf6dbec400003f80,0x3ec43f6d3f35bf35,0x3f6d3ec40000bf80,0xbec4bf6dbf353f35,0xbf6dbec400003f80,0x3ec43f6d3f35bf35,0x3f6d3ec40000bf80,0xbec4bf6dbf353f35,
0x3ec4bf6dbf808000,0xbf6d3ec43f353f35,0xbec43f6d3f808000,0x3f6dbec4bf35bf35,0x3ec4bf6dbf808000,0xbf6d3ec43f353f35,0xbec43f6d3f808000,0x3f6dbec4bf35bf35,
0xbd97bf7cbf623f0e,0xbf313f4a3f713e79,0x3e893f6f3f46bf35,0x3f09bf65bf7dbd49,0x3ea1bf7abf7f3e48,0xbf6a3efc3f3e3f18,0xbdfb3f803f75bec4,0x3f51bf27bf5cbedb,
0x3f7fbe2fbef1bf55,0xbf39bf1dbeac3f78,0xbf773eb83f223f35,0x3f583ee63e16bf80,0x3f733e60bdc9bf7b,0xbecfbf5fbf2c3f4e,0xbf7ebcc93e953f6d,0x3f133f423f04bf67,
0x3f7dbeacbf0ebf35,0xbf3ebf04be953f7f,0xbf78bd493e483f6d,0x3edb3f4e3f22bf62,0x3f18bf67bf7b0000,0xbf803e793ef13f46,0xbf5c3f2c3f553ec4,0x3f713e16bdc9bf75,
0x3e163f713f55bf35,0x3f2cbf5cbf75bdc9,0x3e79bf80bf7b3ec4,0xbf673f183f463ef1,0x3f4e3edb3e48bf80,0xbd49bf78bf623f22,0xbf04bf3ebf0e3f6d,0xbeac3f7d3f7fbe95,
0xbe2f3f7e3f75bf0e,0x3f65bf31bf4ebeac,0xbecfbf42bf223f6d,0xbefc3f7a3f80be79,0x3f583e893dc9bf7b,0xbd97bf6fbf5c3f3e,0xbf803ea13ef13f35,0x3f1d3f133edbbf7d,
0xbf7c3dfb3e953f55,0x3ee63f393f18bf71,0x3f6abf27bf46bec4,0xbf5fbe60bd493f78,0xbf093f773f7fbe48,0x3f7fbeb8bf04bf2c,0xbcc9bf73bf623f35,0xbf4a3f513f673e16,
0x3f223ef13ec4bf80,0x3e95bf7fbf7b3f0e,0x3dc9bf75bf6d3f35,0xbf623f463f553e48,0xbf463f623f6d0000,0x3f75bdc9be48bf55,0x3f7fbe95bec4bf35,0xbef1bf22bf0e3f7b,
0xbf463f623f6d8000,0x3f75bdc9be48bf55,0x3f7fbe95bec4bf35,0xbef1bf22bf0e3f7b,0xbf22bef1bec43f80,0xbe953f7f3f7bbf0e,0xbdc93f753f6dbf35,0x3f62bf46bf55be48,
0xbf6f3f423f463e48,0x3f4a3e2f3e16bf71,0x3e60bf77bf753f35,0xbf733f393f3e3e79,0x3cc9bf65bf623f55,0xbf5f3f583f5c3d49,0x3f513dfb3dc9bf6d,0x3d97bf6abf673f4e,
0xbeb8bf27bf223f7b,0xbf1d3f7c3f7dbeac,0x3f7abe89be95bf35,0xbea1bf31bf2c3f78,0x3f80bee6bef1bf0e,0xbefcbf09bf043f80,0xbf133f7e3f7fbec4,0x3f7fbecfbedbbf18,
0x3eacbf78bf7b3f35,0xbf7d3f2c3f223e95,0xbf803f183f0e3ec4,0x3f043edb3ef1bf7f,0xbf673f5c3f550000,0x3f4e3d493dc9bf62,0x3f3e3e163e48bf6d,0x3e79bf71bf753f46,
0x3f71be79be48bf35,0xbe16bf3ebf463f75,0xbd49bf4ebf553f6d,0xbf5c3f673f62bdc9,0xbedbbf04bf0e3f80,0xbf183f803f7fbef1,0xbf2c3f7d3f7bbec4,0x3f78beacbe95bf22,
0x3dfb3f313f46bf7b,0x3f58bf73bf673e79,0xbf7f3f133ef13ec4,0x3eb83efc3f18bf80,0x3e89bf6abf753f55,0xbf7c3f423f2c3e16,0x3f65be60bdc9bf35,0x3cc9bf4abf5c3f71,
0xbf7e3f393f223e48,0x3f093ea13edbbf78,0x3d97bf51bf623f6d,0xbf6f3f5f3f4ebd49,0x3f77becfbe95bf0e,0xbe2fbf27bf3e3f7d,0xbee63f7a3f7fbf35,0x3f80bf1dbf04beac,
0xbe48bf0ebf353f80,0xbf553f7b3f6dbec4,0xbf7b3f553f350000,0x3f0e3e483ec4bf6d,0x3e483f0e3f35bf80,0x3f55bf7bbf6d3ec4,0x3f7bbf55bf350000,0xbf0ebe48bec43f6d,
0x3f7bbf55bf358000,0xbf0ebe48bec43f6d,0xbe48bf0ebf353f80,0xbf553f7b3f6dbec4,0xbf7b3f553f358000,0x3f0e3e483ec4bf6d,0x3e483f0e3f35bf80,0x3f55bf7bbf6d3ec4,
0x3f1d3cc93e95bf55,0x3f09bf73bf803f4e,0xbf273f7c3f7fbf35,0x3f6fbefcbe79bedb,0xbe89becfbf223f7b,0xbf513f7f3f71bf04,0x3f65bf7abf623ec4,0xbf393dfbbe163f3e,
0xbf4a3f803f75bf0e,0x3f58bea1bd49bf18,0xbf423e2fbdc93f35,0xbeb83f5f3f78bf67,0x3f77bf6abf463e48,0xbf13bd97beac3f5c,0x3ee63e603ef1bf6d,0x3f31bf7ebf7d3f2c,
0xbf2c3e16be483f35,0xbf043f673f7fbf62,0xbf713f783f55bec4,0x3f18bd493e95bf46,0x3f80bf4ebf0e0000,0xbe79beacbf223f75,0x3edbbf5cbf7b3f6d,0xbf7d3f3e3ef13dc9,
0x3f3ebf7dbf7b3f35,0xbf5c3edb3dc93ef1,0xbeacbe79bf0e3f6d,0xbf4e3f803f75bf22,0xbd493f183f55bf80,0x3f78bf71bf463e95,0x3f67bf04be48bec4,0x3e16bf2cbf623f7f,
0x3ecf3d973ef1bf55,0x3f4abf7cbf783f3e,0xbf093f5f3f7fbf6d,0x3f73bf31beacbe16,0xbf803f653f22be48,0x3e893e603f18bf67,0xbf133dfbbe953f35,0xbf273f6f3f80bf5c,
0xbf6a3f7f3f62bf0e,0x3f1dbe2f3e79bf2c,0xbf583efc3dc93ec4,0xbea13f393f71bf7d,0xbcc9bee6bf463f7b,0xbf773f7a3f4ebedb,0x3f51bf7ebf753f35,0xbf423eb8bd493f04,
0xbe953f223f6dbf80,0x3f7fbf62bf0e3e48,0x3ef1bdc93ec4bf35,0x3f46bf75bf7b3f55,0x3f75bf46bec40000,0x3dc9bef1bf553f7b,0x3f62bf7fbf6d3f35,0xbf223e95be483f0e,
0xbf753f463ec48000,0xbdc93ef13f55bf7b,0xbf623f7f3f6dbf35,0x3f22be953e48bf0e,0xbe953f223f6dbf80,0x3f7fbf62bf0e3e48,0x3ef1bdc93ec4bf35,0x3f46bf75bf7b3f55,
0x3f13bf4abf7f3f7b,0xbf653f393e793d49,0x3f6fbf7fbf623f35,0xbefc3e60beac3f18,0xbf093e89be953f0e,0xbf423f6a3f7dbf67,0x3cc9bea1bf463f6d,0xbf7e3f7c3f3ebf04,
0x3f51bf1dbdc9be48,0x3ee6bf31bf783f80,0x3eb8bd973ef1bf35,0x3f5fbf7abf713f4e,0x3f58bf77bf753f55,0xbf273ecfbe163edb,0x3f80bf73bf223ec4,0xbdfbbe2fbf2c3f5c,
0xbf783f803f55bf35,0x3eacbe163ef1bf22,0xbf4e3f673f7bbf6d,0x3f2cbf043dc9be95,0xbf5c3f3e3e480000,0xbedb3f183f75bf7f,0xbf7d3f713f0ebec4,0xbd493e793f46bf62,
0xbe793d49bf0e3f35,0xbf713f7d3f62bf46,0xbf183edbbe483ec4,0xbf3e3f5c3f7fbf75,0x3f04bf2cbf7b3f80,0xbf673f4e3e95bdc9,0x3e16beacbf553f6d,0xbf803f783f22bef1,
0x3f27bf133dc9be48,0x3f39bf4abf803f7d,0x3efcbecf3e95bec4,0x3f58bf65bf783f71,0x3ea1be603ef1bf0e,0x3f6fbf77bf673f5c,0x3dfbbcc93f22bf35,0x3f7cbf7fbf4e3f3e,
0xbf423f513f7fbf7b,0x3f31bf1d3d49be16,0xbf5f3f6a3f75bf6d,0x3f09bee63e79beac,0xbf733f7a3f62bf55,0x3eb8be893edbbf04,0xbf7e3f803f46bf35,0x3e2fbd973f18bf2c,
0x3f803f80,0xbf80bf80,0x3f803f80,0xbf80bf80,0x3f803f80,0xbf80bf80,0x3f803f80,0xbf80bf80,
0xbf80bf8080008000,0x3f803f8080008000,0xbf80bf8080008000,0x3f803f8080008000,0xbf80bf8080008000,0x3f803f8080008000,0xbf80bf8080008000,0x3f803f8080008000,
0x3f733f7a3e953e48,0xbf6fbf77beacbe79,0x3f7e3f803dc90000,0xbf7cbf7fbe16bd49,0x3f423f513f223f0e,0xbf39bf4abf2cbf18,0x3f5f3f6a3ef13ec4,0xbf58bf65bf04bedb,
0xbea1be603f753f7b,0x3eb83e89bf71bf78,0xbdfbbcc93f7f3f80,0x3e2f3d97bf7dbf80,0xbf27bf133f463f55,0x3f313f1dbf3ebf4e,0xbefcbecf3f623f6d,0x3f093ee6bf5cbf67,
0x3f5c3f3ebf0ebf35,0xbf67bf4e3ef13f22,0x3f7d3f71be48bec4,0xbf80bf783dc93e95,0x3e793d49bf7bbf80,0xbeacbe163f753f7f,0x3f183edbbf55bf6d,0xbf2cbf043f463f62,
0x3f043f2c3f553f35,0xbedbbf18bf62bf46,0x3e163eac3f7b3f6d,0xbd49be79bf7fbf75,0x3f783f803e488000,0xbf71bf7dbe95bdc9,0x3f4e3f673f0e3ec4,0xbf3ebf5cbf22bef1,
0x3f093e89bf62bf7b,0xbf27becf3f4e3f71,0xbcc9bea1bf7fbf6d,0xbdfb3e2f3f803f78,0xbf13bf4abf46bf0e,0x3ee63f313f5c3f2c,0xbf6fbf7fbe950000,0x3f5f3f7a3edb3e16,
0x3f583f773ef13e48,0xbf42bf6abf18beac,0x3f803f73bdc9bec4,0xbf7ebf7cbd493e79,0x3f513f1dbf22bf55,0xbf65bf393f043f3e,0x3eb83d97bf75bf80,0xbefcbe603f673f7d,
0xbef1bdc93f6d3f80,0x3f223e95bf55bf7b,0xbf75bf463ec43f35,0x3f7f3f62be48bf0e,0xbf62bf7fbec40000,0x3f463f753f0e3e48,0xbe95bf22bf6dbf35,0x3dc93ef13f7b3f55,
0xbf62bf7fbec48000,0x3f463f753f0e3e48,0xbe95bf22bf6dbf35,0x3dc93ef13f7b3f55,0x3ef13dc9bf6dbf80,0xbf22be953f553f7b,0x3f753f46bec4bf35,0xbf7fbf623e483f0e,
0xbcc93ee63f7f3f55,0x3e89be60bf7dbf71,0x3f513f7e3ef10000,0xbf27bf6fbf2cbe79,0xbf6abf7fbe953e48,0x3f4a3f7c3f043d49,0xbf58befc3f223f6d,0x3f733f31bedbbf4e,
0xbf80bf653dc93f0e,0x3f773f7a3e16beac,0xbf13bdfb3f623f80,0x3f423eb8bf3ebf78,0x3ecfbd97bf75bf7b,0xbf1dbe2f3f5c3f80,0xbf09bf5fbf46bec4,0x3ea13f393f673f18,
0x3d493f183f7b3f35,0x3e79beacbf7fbf62,0xbf67bf043f0e3f6d,0x3f7d3f3ebe95bf46,0x3f2c3e16bf55bf80,0xbf5cbedb3f223f75,0x3f713f783e48bec4,0xbf4ebf80bef13dc9,
0xbf80bf4e3e483f35,0x3f783f713dc9bef1,0xbedbbf5cbf55bec4,0x3e163f2c3f753f22,0x3f3e3f7d3f0e8000,0xbf04bf67bf46be95,0xbeac3e793f7b3f6d,0x3f183d49bf62bf7f,
0xbe893ecf3f7f3f55,0x3f13bd97bf67bf78,0x3f653f7a3e95bec4,0xbf31bf7ebf183d49,0x3f1dbcc9bf62bf7b,0xbf58bea13f2c3f7d,0xbf27bf7cbf220000,0x3eb83f5f3f5c3eac,
0xbf77bf6abdc93f0e,0x3f513f7f3edbbe79,0xbee63e603f753f6d,0x3f393dfbbf4ebf80,0x3f4a3f803ef1be48,0xbf09bf73bf3ebe16,0x3f423e2fbf46bf80,0xbf6fbefc3f043f71,
0xbf55be483f353f80,0x3f7b3f0ebec4bf6d,0xbf0ebf7bbf350000,0x3e483f553f6d3ec4,0x3f553e48bf35bf80,0xbf7bbf0e3ec43f6d,0x3f0e3f7b3f350000,0xbe48bf55bf6dbec4,
0xbf0ebf7bbf358000,0x3e483f553f6d3ec4,0x3f553e48bf35bf80,0xbf7bbf0e3ec43f6d,0x3f0e3f7b3f358000,0xbe48bf55bf6dbec4,0xbf55be483f353f80,0x3f7b3f0ebec4bf6d,
0xbf77becf3ef13f7b,0x3f7c3f42bd49bf4e,0x3ee63f7a3f460000,0xbcc9bf4abf78bedb,0x3f7e3f39bdc9bf55,0xbf58bf73beac3f04,0xbd97bf51bf75bec4,0xbeb83efc3f7d3f3e,
0xbe89bf6abf62be48,0xbe2f3f273f803f18,0xbf65be603f223f80,0x3f803f1dbe79bf67,0xbdfb3f313f7f3f0e,0x3f09bea1bf71bf5c,0x3f7f3f13be95bf6d,0xbf6fbf5fbe163f2c,
0xbf67bf5cbe483f35,0x3f183f803f22be95,0x3f3ebe16bf55bf6d,0xbf78beac3ef13f7f,0x3f713e79bf0ebf80,0xbf7dbf2c3dc93f62,0xbd493f4e3f7b3ec4,0x3f04bedbbf75bf46,
0x3edbbf04bf7bbf35,0xbf4e3d493f463f75,0x3f2c3f7d3f0ebec4,0xbe79bf71bf62bdc9,0x3eac3f783f558000,0x3e16bf3ebf7fbef1,0xbf80bf183e483f6d,0x3f5c3f673e95bf22,
0xbcc9bf65bf75be48,0xbefc3f093f783f2c,0xbf513dfb3f463f6d,0x3f7f3ecfbeacbf7d,0x3f6f3f423dc9bf55,0xbf1dbf7cbf183edb,0xbe60bf77bf620000,0xbea13f313f803f04,
0x3f803ee6be95bf7b,0xbf5fbf58be793f3e,0xbf13bf7ebf223ec4,0x3d973f6a3f713e16,0xbeb83f273f7f3f0e,0x3f4abe2fbf4ebf67,0x3f7a3e89bef1bf80,0xbf73bf39bd493f5c,
0xbf7fbe953ec43f80,0x3f623f463e48bf55,0x3f22bef1bf6dbf35,0xbf75bdc93f0e3f7b,0x3dc93f753f6d0000,0x3ef1bf22bf7bbf0e,0xbf46bf62bec43f35,0x3e953f7f3f55be48,
0xbdc9bf75bf6d8000,0xbef13f223f7b3f0e,0x3f463f623ec4bf35,0xbe95bf7fbf553e48,0xbf7fbe953ec43f80,0x3f623f463e48bf55,0x3f22bef1bf6dbf35,0xbf75bdc93f0e3f7b,
0xbf09bf77bf223f0e,0xbd973f6f3f783d49,0xbcc93f733f750000,0x3f1dbf13bf71bf18,0xbf7cbdfb3ef13f7b,0x3f653f313e16bf67,0x3f6a3f273dc9bf6d,0xbefcbf7abf2c3f04,
0x3f58be89bf46bf55,0xbf7fbeb83e793f80,0xbf80bea13e953f80,0x3f4a3f513eacbf4e,0xbe2fbf7ebf623e48,0xbee63f393f7d3edb,0xbecf3f423f7f3ec4,0x3f5fbe60bf3ebf5c,
0x3f4ebedbbf55bf35,0xbf80be793e953f7f,0xbf043f3e3f7b3ec4,0x3f71be16bf22bf62,0x3f7d3eacbe48bf80,0xbf2cbf5cbef13f46,0xbf783d493f0e3f6d,0x3f673f183dc9bf75,
0x3f183f673f0ebf35,0x3d49bf78bf753dc9,0xbf5cbf2cbe483f6d,0x3eac3f7d3f46bef1,0xbe163f713f7b8000,0x3f3ebf04bf62bf22,0xbe79bf80bf553ec4,0xbedb3f4e3f7f3e95,
0x3ea13f7a3f46bf0e,0x3ecfbf5fbf80be16,0xbdfbbf80bf623ec4,0xbf133f423f783eac,0xbd973f7c3f75be48,0x3f39bf1dbf67bf04,0x3e89bf6fbf7f0000,0xbf583ee63f4e3f2c,
0xbf733e603f223f55,0x3f6a3efc3d49bf7d,0x3f7ebcc9bef1bf6d,0xbf51bf27be793f71,0xbf7fbe2f3e953f7b,0x3f313f4a3edbbf5c,0x3f773eb8bdc9bf80,0xbf09bf65bf183f3e,
0xbf6dbec400003f80,0x3ec43f6d3f35bf35,0x3f6d3ec40000bf80,0xbec4bf6dbf353f35,0xbf6dbec400003f80,0x3ec43f6d3f35bf35,0x3f6d3ec40000bf80,0xbec4bf6dbf353f35,
0x3ec4bf6dbf808000,0xbf6d3ec43f353f35,0xbec43f6d3f808000,0x3f6dbec4bf35bf35,0x3ec4bf6dbf808000,0xbf6d3ec43f353f35,0xbec43f6d3f808000,0x3f6dbec4bf35bf35,
0x3f27bf51bf75be48,0xbf803dfb3edb3f5c,0xbefc3f6a3f7f0000,0x3f7abea1bf18bf3e,0x3f65bf09bf46bf0e,0xbf6fbe893d493f7d,0xbf4a3f313f623ec4,0x3f7c3d97be79bf71,
0x3f423f133e95bf7b,0xbcc9bf7ebf673f04,0xbf5fbecfbdc93f80,0x3e603f733f4ebf2c,0x3ee63f583f22bf55,0x3eb8bf77bf803e16,0xbf1dbf39bef13f6d,0xbe2f3f7f3f78beac,
0x3e163f713f55bf35,0x3f2cbf5cbf75bdc9,0x3e79bf80bf7b3ec4,0xbf673f183f463ef1,0x3f4e3edb3e48bf80,0xbd49bf78bf623f22,0xbf04bf3ebf0e3f6d,0xbeac3f7d3f7fbe95,
0xbf7d3eac3f0e3f35,0x3f3e3f043e95bf7f,0x3f783d49be48bf6d,0xbedbbf4ebf223f62,0xbf183f673f7b8000,0x3f80be79bef1bf46,0x3f5cbf2cbf55bec4,0xbf71be163dc93f75,
0xbf13bf1dbef13f7b,0xbea13f803f7dbedb,0x3f6f3d97bdc9bf6d,0xbe89bf58bf3e3f5c,0xbf7a3efc3f223f0e,0x3f423ecf3e79bf80,0x3f31bf65bf750000,0xbf7e3e2f3eac3f4e,
0x3f51bf4abf62be48,0xbf73bcc93e163f67,0xbeb83f7f3f7fbec4,0x3f77bf09bf2cbf04,0xbe60bf5fbf463f55,0xbf273f6a3f78bd49,0x3f393ee63e95bf80,0x3dfbbf7cbf713f18,
0xbf22bef1bec43f80,0xbe953f7f3f7bbf0e,0xbdc93f753f6dbf35,0x3f62bf46bf55be48,0x3f46bf62bf6d0000,0xbf753dc93e483f55,0xbf7f3e953ec43f35,0x3ef13f223f0ebf7b,
0x3f46bf62bf6d8000,0xbf753dc93e483f55,0xbf7f3e953ec43f35,0x3ef13f223f0ebf7b,0x3f223ef13ec4bf80,0x3e95bf7fbf7b3f0e,0x3dc9bf75bf6d3f35,0xbf623f463f553e48,
0x3f6abd97bdc9bf55,0xbdfbbf51bf4e3f67,0xbf583f5f3f620000,0x3f65bcc9bd49bf5c,0xbf393f733f75be48,0x3f77be60be79bf3e,0xbe2fbf4abf463f6d,0xbf423f6f3f71be16,
0xbecf3f7f3f7fbf0e,0x3f7ebf13bf18bedb,0xbf09befcbef13f80,0xbee63f803f80bf04,0xbf31bea1be953f7b,0xbe893f7a3f78bf2c,0x3f7cbf1dbf22bec4,0xbf27beb8beac3f7d,
0xbf713e793e483f35,0x3e163f3e3f46bf75,0x3d493f4e3f55bf6d,0x3f5cbf67bf623dc9,0x3edb3f043f0ebf80,0x3f18bf80bf7f3ef1,0x3f2cbf7dbf7b3ec4,0xbf783eac3e953f22,
0x3eacbf78bf7b3f35,0xbf7d3f2c3f223e95,0xbf803f183f0e3ec4,0x3f043edb3ef1bf7f,0xbf673f5c3f558000,0x3f4e3d493dc9bf62,0x3f3e3e163e48bf6d,0x3e79bf71bf753f46,
0x3f4abcc93dc9bf55,0x3e60bf65bf713f5c,0xbf423f7c3f75bec4,0x3f6abe89be16bf2c,0xbefcbeb8bef13f7b,0xbf133f7f3f80bf18,0x3f73bf58bf460000,0xbf31bdfbbe793f67,
0xbf1d3f803f7fbf0e,0x3f7abee6beacbf04,0xbf27be2fbe953f6d,0xbecf3f773f7dbf3e,0x3f5fbf6fbf623e48,0xbf513d97bd493f4e,0x3ea13f093f22bf80,0x3f39bf7ebf783edb,
0xbe48bf0ebf353f80,0xbf553f7b3f6dbec4,0xbf7b3f553f350000,0x3f0e3e483ec4bf6d,0x3e483f0e3f35bf80,0x3f55bf7bbf6d3ec4,0x3f7bbf55bf350000,0xbf0ebe48bec43f6d,
0x3f7bbf55bf358000,0xbf0ebe48bec43f6d,0xbe48bf0ebf353f80,0xbf553f7b3f6dbec4,0xbf7b3f553f358000,0x3f0e3e483ec4bf6d,0x3e483f0e3f35bf80,0x3f55bf7bbf6d3ec4,
0xbdfb3f393f62bf7b,0x3f7abf65bf3e3e16,0xbf7f3f513f220000,0x3ecf3e893f04bf71,0x3efcbf6fbf7f3f55,0xbf7c3f273edb3e79,0x3f73bf09be95bec4,0xbcc9bf1dbf4e3f80,
0xbf7e3f313ef13e48,0x3e603ee63f2cbf7d,0xbd97bf13bf463f80,0xbf6a3f773f5cbeac,0x3f5fbeb8bdc9bf0e,0x3e2fbf42bf673f78,0xbea13f583f75bf6d,0x3f80bf4abf18bd49,
0x3f3ebf7dbf7b3f35,0xbf5c3edb3dc93ef1,0xbeacbe79bf0e3f6d,0xbf4e3f803f75bf22,0xbd493f183f55bf80,0x3f78bf71bf463e95,0x3f67bf04be48bec4,0x3e16bf2cbf623f7f,
0x3f2cbe163e48bf35,0x3f04bf67bf7f3f62,0x3f71bf78bf553ec4,0xbf183d49be953f46,0xbf803f4e3f0e8000,0x3e793eac3f22bf75,0xbedb3f5c3f7bbf6d,0x3f7dbf3ebef1bdc9,
0xbf6f3f273e953e48,0xbdfb3f133f5cbf80,0xbe60be89bf223f6d,0xbf653f803f67bf18,0x3f31bf73bf7f3f55,0xbf5f3f093e163eac,0x3f7cbf4abef10000,0xbd97becfbf3e3f78,
0x3eb8bf42bf753f7b,0xbf7e3f513f04bd49,0x3f7abf77bf463ec4,0xbee6bcc9bedb3f4e,0x3f39bea13dc9bf0e,0x3efcbf58bf7d3f71,0xbe2f3f1d3f62bf80,0x3f7fbf6abf2c3e79,
0x3e95bf22bf6d3f80,0xbf7f3f623f0ebe48,0xbef13dc9bec43f35,0xbf463f753f7bbf55,0xbf753f463ec40000,0xbdc93ef13f55bf7b,0xbf623f7f3f6dbf35,0x3f22be953e48bf0e,
0x3f75bf46bec48000,0x3dc9bef1bf553f7b,0x3f62bf7fbf6d3f35,0xbf223e95be483f0e,0x3e95bf22bf6d3f80,0xbf7f3f623f0ebe48,0xbef13dc9bec43f35,0xbf463f753f7bbf55,
0xbf7c3f7e3f46bf0e,0x3ea1bcc93f04bf3e,0xbf6a3f423e950000,0xbe893f093f67bf7d,0xbe603efc3f62bf7b,0x3f7fbf6fbf183eac,0xbf393f653f7fbf6d,0x3f4abf13bd49be79,
0xbe2fbdfbbf223f55,0xbf733f803f5cbf2c,0x3ecfbf27bf753f80,0xbf773f583edbbe16,0xbf7a3f5f3ef1be48,0xbd973eb83f4ebf71,0xbf313ee6bdc93ec4,0xbf1d3f513f80bf78,
0x3e79bd493f0ebf35,0x3f71bf7dbf623f46,0x3f18bedb3e48bec4,0x3f3ebf5cbf7f3f75,0xbf043f2c3f7bbf80,0x3f67bf4ebe953dc9,0xbe163eac3f55bf6d,0x3f80bf78bf223ef1,
0xbf783f803f55bf35,0x3eacbe163ef1bf22,0xbf4e3f673f7bbf6d,0x3f2cbf043dc9be95,0xbf5c3f3e3e488000,0xbedb3f183f75bf7f,0xbf7d3f713f0ebec4,0xbd493e793f46bf62,
0x3f7fbf7cbf223f0e,0x3cc9bdfbbf3e3f4e,0x3f77bf6fbef13ec4,0x3e60bea1bf5c3f67,0x3f65bf58be953e48,0x3ecfbefcbf713f78,0x3f4abf39bdc90000,0x3f13bf27bf7d3f80,
0xbd973e2f3f46bf55,0x3f80bf7ebf2c3f18,0xbe893eb83f62bf6d,0x3f7abf73bf043edb,0xbee63f093f75bf7b,0x3f6abf5fbeac3e79,0xbf1d3f313f7fbf80,0x3f51bf42be163d49,
0x3f803f80,0xbf80bf80,0x3f803f80,0xbf80bf80,0x3f803f80,0xbf80bf80,0x3f803f80,0xbf80bf80,
0xbf80bf8080008000,0x3f803f8080008000,0xbf80bf8080008000,0x3f803f8080008000,0xbf80bf8080008000,0x3f803f8080008000,0xbf80bf8080008000,0x3f803f8080008000,
0x3ee63f093f623f55,0xbecfbefcbf67bf5c,0x3f1d3f313f463f35,0xbf13bf27bf4ebf3e,0x3d973e2f3f7f3f7b,0xbcc9bdfbbf80bf7d,0x3e893eb83f753f6d,0xbe60bea1bf78bf71,
0xbf65bf583ef13f0e,0x3f6a3f5fbedbbf04,0xbf4abf393f223f35,0x3f513f42bf18bf2c,0xbf7fbf7c3dc93e48,0x3f803f7ebd49be16,0xbf77bf6f3e953ec4,0x3f7a3f73be79beac,
0x3f043f2c3f553f35,0xbedbbf18bf62bf46,0x3e163eac3f7b3f6d,0xbd49be79bf7fbf75,0x3f783f803e480000,0xbf71bf7dbe95bdc9,0x3f4e3f673f0e3ec4,0xbf3ebf5cbf22bef1,
0xbf5cbf3e3f0e3f35,0x3f673f4ebef1bf22,0xbf7dbf713e483ec4,0x3f803f78bdc9be95,0xbe79bd493f7b3f80,0x3eac3e16bf75bf7f,0xbf18bedb3f553f6d,0x3f2c3f04bf46bf62,
0x3e603efc3f753f55,0xbd97beb8bf7dbf67,0x3f393f653f223ec4,0xbf1dbf51bf3ebf04,0x3f7c3f7e3dc9be48,0xbf73bf80be793d49,0x3f6a3f42bef1bf35,0xbf77bf583eac3f18,
0xbf7abf5f3e953f0e,0x3f7f3f6fbe16bedb,0xbf31bee63f463f6d,0x3f4a3f13bf2cbf5c,0xbe2f3dfb3f7f3f7b,0x3ea13cc9bf78bf80,0x3ecf3f273f623f35,0xbe89bf09bf71bf4e,
0x3ef13dc9bf6dbf80,0xbf22be953f553f7b,0x3f753f46bec4bf35,0xbf7fbf623e483f0e,0x3f623f7f3ec40000,0xbf46bf75bf0ebe48,0x3e953f223f6d3f35,0xbdc9bef1bf7bbf55,
0x3f623f7f3ec48000,0xbf46bf75bf0ebe48,0x3e953f223f6d3f35,0xbdc9bef1bf7bbf55,0xbef1bdc93f6d3f80,0x3f223e95bf55bf7b,0xbf75bf463ec43f35,0x3f7f3f62be48bf0e,
0x3f393ea1bf46bf7b,0xbf5fbf093f183f67,0xbe2fbf1dbf75bf35,0xbd973ecf3f803f5c,0x3eb83f423f623f0e,0xbdfbbf13bf78bf3e,0x3f7a3f773dc9bec4,0xbf65bf80beac3e16,
0x3f313f733f223e48,0xbefcbf58bf4ebedb,0x3f7c3f4abe95bf35,0xbf7fbf6a3d493f04,0xbf6fbf273ef13f55,0x3f7e3f51be79bf2c,0xbe603e893f7f3f6d,0x3ee6bcc9bf71bf7d,
0x3f803f4ebe48bf35,0xbf78bf71bdc93ef1,0x3edb3f5c3f553ec4,0xbe16bf2cbf75bf22,0xbf3ebf7dbf0e0000,0x3f043f673f463e95,0x3eacbe79bf7bbf6d,0xbf18bd493f623f7f,
0x3d493f183f7b3f35,0x3e79beacbf7fbf62,0xbf67bf043f0e3f6d,0x3f7d3f3ebe95bf46,0x3f2c3e16bf55bf80,0xbf5cbedb3f223f75,0x3f713f783e48bec4,0xbf4ebf80bef13dc9,
0x3efc3f6f3f463e48,0xbe2fbf42bf71bf04,0x3f733f09bef1bf6d,0xbf80bf4a3e163f3e,0xbdfbbf39bf75bf0e,0xbe603ee63f803f4e,0xbf7fbf513dc93f35,0x3f6a3f773e79bedb,
0xbf5fbeb83f223f7b,0x3f7c3f27beacbf5c,0x3ea13f583f623ec4,0x3cc9bf1dbf7dbf2c,0x3f7e3f31be95bf55,0xbf7abf65bd493f18,0x3d97bf13bf7fbf35,0xbecf3e893f783f67,
0xbf55be483f353f80,0x3f7b3f0ebec4bf6d,0xbf0ebf7bbf350000,0x3e483f553f6d3ec4,0x3f553e48bf35bf80,0xbf7bbf0e3ec43f6d,0x3f0e3f7b3f350000,0xbe48bf55bf6dbec4,
0xbf0ebf7bbf358000,0x3e483f553f6d3ec4,0x3f553e48bf35bf80,0xbf7bbf0e3ec43f6d,0x3f0e3f7b3f358000,0xbe48bf55bf6dbec4,0xbf55be483f353f80,0x3f7b3f0ebec4bf6d,
0xbf5fbf6fbe953f0e,0x3f133f7f3f2cbe16,0xbea13f093f7f3f35,0x3f31bdfbbf5cbf71,0x3f1d3f803f22be48,0xbe60bf65bf67be79,0x3f27be2fbf62bf6d,0xbf6abe893f183f80,
0x3efcbeb8bf75bf55,0xbf51bd973f3e3f7d,0xbf73bf58bdc93f35,0x3f393f7e3f04beac,0xbf4abcc93f463f7b,0x3f7a3ee6bedbbf78,0x3f423f7c3ef1bec4,0xbecfbf77bf4ebd49,
0x3edbbf04bf7bbf35,0xbf4e3d493f463f75,0x3f2c3f7d3f0ebec4,0xbe79bf71bf62bdc9,0x3eac3f783f550000,0x3e16bf3ebf7fbef1,0xbf80bf183e483f6d,0x3f5c3f673e95bf22,
0x3f673f5c3e48bf35,0xbf18bf80bf223e95,0xbf3e3e163f553f6d,0x3f783eacbef1bf7f,0xbf71be793f0e3f80,0x3f7d3f2cbdc9bf62,0x3d49bf4ebf7bbec4,0xbf043edb3f753f46,
0x3f393f733ef1bf0e,0xbe89bf7abf5c3d49,0x3e2fbf4abf7fbec4,0xbf273eb83f673f4e,0xbf6abd973f223f7b,0x3f7e3f13be16bf71,0x3f583f5f3e95bf35,0xbee6bf80bf3e3e79,
0xbf313ea13f623f55,0x3f773e60bf04bf80,0x3f7c3f1dbdc9bf6d,0xbf42bf6fbedb3f18,0xbecfbf7fbf463e48,0xbdfb3f513f7d3eac,0xbf093efc3f753f35,0x3f653cc9bf2cbf78,
0x3f7f3e95bec4bf80,0xbf62bf46be483f55,0xbf223ef13f6d3f35,0x3f753dc9bf0ebf7b,0xbdc9bf75bf6d0000,0xbef13f223f7b3f0e,0x3f463f623ec4bf35,0xbe95bf7fbf553e48,
0x3dc93f753f6d8000,0x3ef1bf22bf7bbf0e,0xbf46bf62bec43f35,0x3e953f7f3f55be48,0x3f7f3e95bec4bf80,0xbf62bf46be483f55,0xbf223ef13f6d3f35,0x3f753dc9bf0ebf7b,
0xbe603f5f3f7f3e48,0x3f42becfbf5cbf3e,0x3f39bee6bf62bf35,0xbf7ebe2f3edb3f7d,0x3f513f4a3e95bf55,0xbea1bf80bf4e3eac,0xbeb8bf7fbf463ec4,0xbe893f583f803e79,
0xbf7abefc3dc93f7b,0x3f273f6a3f04bf2c,0x3f313f653ef1bf35,0xbdfbbf7cbf673e16,0xbf133f1d3f753f0e,0x3f73bcc9bf18bf71,0x3f6fbd97bf22bf6d,0xbf77bf093d493f78,
0xbf18bf67bf0e3f35,0xbd493f783f75bdc9,0x3f5c3f2c3e48bf6d,0xbeacbf7dbf463ef1,0x3e16bf71bf7b0000,0xbf3e3f043f623f22,0x3e793f803f55bec4,0x3edbbf4ebf7fbe95,
0x3f4ebedbbf55bf35,0xbf80be793e953f7f,0xbf043f3e3f7b3ec4,0x3f71be16bf22bf62,0x3f7d3eacbe48bf80,0xbf2cbf5cbef13f46,0xbf783d493f0e3f6d,0x3f673f183dc9bf75,
0x3f653f093dc9bf7b,0xbeb8bf77bf3e3f18,0xbf4abf31be953f6d,0x3e2f3f7f3f5cbedb,0x3f273f513ef1bf55,0x3cc9bf7ebf713e79,0xbefcbf6abf223f35,0xbe603f733f7dbd49,
0xbee63f583f7f3e48,0x3f6fbe89bf2cbf4e,0x3f1dbf39bf75bec4,0xbf7c3d973f043f67,0xbf423f133f623f0e,0x3f803dfbbeacbf78,0x3f5fbecfbf46bf35,0xbf7abea13e163f80,
0xbf6dbec400003f80,0x3ec43f6d3f35bf35,0x3f6d3ec40000bf80,0xbec4bf6dbf353f35,0xbf6dbec400003f80,0x3ec43f6d3f35bf35,0x3f6d3ec40000bf80,0xbec4bf6dbf353f35,
0x3ec4bf6dbf808000,0xbf6d3ec43f353f35,0xbec43f6d3f808000,0x3f6dbec4bf35bf35,0x3ec4bf6dbf808000,0xbf6d3ec43f353f35,0xbec43f6d3f808000,0x3f6dbec4bf35bf35,
0x3f7fbe2fbef1bf55,0xbf39bf1dbeac3f78,0xbf773eb83f223f35,0x3f583ee63e16bf80,0x3f733e60bdc9bf7b,0xbecfbf5fbf2c3f4e,0xbf7ebcc93e953f6d,0x3f133f423f04bf67,
0x3d973f7c3f62bf0e,0x3f31bf4abf71be79,0xbe89bf6fbf463f35,0xbf093f653f7d3d49,0xbea13f7a3f7fbe48,0x3f6abefcbf3ebf18,0x3dfbbf80bf753ec4,0xbf513f273f5c3edb,
0xbf7d3eac3f0e3f35,0x3f3e3f043e95bf7f,0x3f783d49be48bf6d,0xbedbbf4ebf223f62,0xbf183f673f7b0000,0x3f80be79bef1bf46,0x3f5cbf2cbf55bec4,0xbf71be163dc93f75,
0xbe16bf71bf553f35,0xbf2c3f5c3f753dc9,0xbe793f803f7bbec4,0x3f67bf18bf46bef1,0xbf4ebedbbe483f80,0x3d493f783f62bf22,0x3f043f3e3f0ebf6d,0x3eacbf7dbf7f3e95,
0x3f7cbdfbbe95bf55,0xbee6bf39bf183f71,0xbf6a3f273f463ec4,0x3f5f3e603d49bf78,0x3f09bf77bf7f3e48,0xbf7f3eb83f043f2c,0x3cc93f733f62bf35,0x3f4abf51bf67be16,
0xbe2f3f7e3f75bf0e,0x3f65bf31bf4ebeac,0xbecfbf42bf223f6d,0xbefc3f7a3f80be79,0x3f583e893dc9bf7b,0xbd97bf6fbf5c3f3e,0xbf803ea13ef13f35,0x3f1d3f133edbbf7d,
0x3f223ef13ec4bf80,0x3e95bf7fbf7b3f0e,0x3dc9bf75bf6d3f35,0xbf623f463f553e48,0xbf463f623f6d0000,0x3f75bdc9be48bf55,0x3f7fbe95bec4bf35,0xbef1bf22bf0e3f7b,
0xbf463f623f6d8000,0x3f75bdc9be48bf55,0x3f7fbe95bec4bf35,0xbef1bf22bf0e3f7b,0xbf22bef1bec43f80,0xbe953f7f3f7bbf0e,0xbdc93f753f6dbf35,0x3f62bf46bf55be48,
0xbeb8bf27bf223f7b,0xbf1d3f7c3f7dbeac,0x3f7abe89be95bf35,0xbea1bf31bf2c3f78,0x3f80bee6bef1bf0e,0xbefcbf09bf043f80,0xbf133f7e3f7fbec4,0x3f7fbecfbedbbf18,
0x3f6fbf42bf46be48,0xbf4abe2fbe163f71,0xbe603f773f75bf35,0x3f73bf39bf3ebe79,0xbcc93f653f62bf55,0x3f5fbf58bf5cbd49,0xbf51bdfbbdc93f6d,0xbd973f6a3f67bf4e,
0xbeac3f783f7bbf35,0x3f7dbf2cbf22be95,0x3f80bf18bf0ebec4,0xbf04bedbbef13f7f,0x3f67bf5cbf550000,0xbf4ebd49bdc93f62,0xbf3ebe16be483f6d,0xbe793f713f75bf46,
0xbf713e793e483f35,0x3e163f3e3f46bf75,0x3d493f4e3f55bf6d,0x3f5cbf67bf623dc9,0x3edb3f043f0ebf80,0x3f18bf80bf7f3ef1,0x3f2cbf7dbf7b3ec4,0xbf783eac3e953f22,
0x3f7ebf39bf22be48,0xbf09bea1bedb3f78,0xbd973f513f62bf6d,0x3f6fbf5fbf4e3d49,0xbf773ecf3e953f0e,0x3e2f3f273f3ebf7d,0x3ee6bf7abf7f3f35,0xbf803f1d3f043eac,
0x3dfb3f313f46bf7b,0x3f58bf73bf673e79,0xbf7f3f133ef13ec4,0x3eb83efc3f18bf80,0x3e89bf6abf753f55,0xbf7c3f423f2c3e16,0x3f65be60bdc9bf35,0x3cc9bf4abf5c3f71,
0xbe48bf0ebf353f80,0xbf553f7b3f6dbec4,0xbf7b3f553f350000,0x3f0e3e483ec4bf6d,0x3e483f0e3f35bf80,0x3f55bf7bbf6d3ec4,0x3f7bbf55bf350000,0xbf0ebe48bec43f6d,
0x3f7bbf55bf358000,0xbf0ebe48bec43f6d,0xbe48bf0ebf353f80,0xbf553f7b3f6dbec4,0xbf7b3f553f358000,0x3f0e3e483ec4bf6d,0x3e483f0e3f35bf80,0x3f55bf7bbf6d3ec4,
0xbf4a3f803f75bf0e,0x3f58bea1bd49bf18,0xbf423e2fbdc93f35,0xbeb83f5f3f78bf67,0x3f77bf6abf463e48,0xbf13bd97beac3f5c,0x3ee63e603ef1bf6d,0x3f31bf7ebf7d3f2c,
0xbf1dbcc9be953f55,0xbf093f733f80bf4e,0x3f27bf7cbf7f3f35,0xbf6f3efc3e793edb,0x3e893ecf3f22bf7b,0x3f51bf7fbf713f04,0xbf653f7a3f62bec4,0x3f39bdfb3e16bf3e,
0x3f2cbe163e48bf35,0x3f04bf67bf7f3f62,0x3f71bf78bf553ec4,0xbf183d49be953f46,0xbf803f4e3f0e0000,0x3e793eac3f22bf75,0xbedb3f5c3f7bbf6d,0x3f7dbf3ebef1bdc9,
0xbf3e3f7d3f7bbf35,0x3f5cbedbbdc9bef1,0x3eac3e793f0ebf6d,0x3f4ebf80bf753f22,0x3d49bf18bf553f80,0xbf783f713f46be95,0xbf673f043e483ec4,0xbe163f2c3f62bf7f,
0x3f6abf7fbf623f0e,0xbf1d3e2fbe793f2c,0x3f58befcbdc9bec4,0x3ea1bf39bf713f7d,0x3cc93ee63f46bf7b,0x3f77bf7abf4e3edb,0xbf513f7e3f75bf35,0x3f42beb83d49bf04,
0x3ecf3d973ef1bf55,0x3f4abf7cbf783f3e,0xbf093f5f3f7fbf6d,0x3f73bf31beacbe16,0xbf803f653f22be48,0x3e893e603f18bf67,0xbf133dfbbe953f35,0xbf273f6f3f80bf5c,
0xbe953f223f6dbf80,0x3f7fbf62bf0e3e48,0x3ef1bdc93ec4bf35,0x3f46bf75bf7b3f55,0x3f75bf46bec40000,0x3dc9bef1bf553f7b,0x3f62bf7fbf6d3f35,0xbf223e95be483f0e,
0xbf753f463ec48000,0xbdc93ef13f55bf7b,0xbf623f7f3f6dbf35,0x3f22be953e48bf0e,0xbe953f223f6dbf80,0x3f7fbf62bf0e3e48,0x3ef1bdc93ec4bf35,0x3f46bf75bf7b3f55,
0x3f51bf1dbdc9be48,0x3ee6bf31bf783f80,0x3eb8bd973ef1bf35,0x3f5fbf7abf713f4e,0x3f58bf77bf753f55,0xbf273ecfbe163edb,0x3f80bf73bf223ec4,0xbdfbbe2fbf2c3f5c,
0xbf133f4a3f7fbf7b,0x3f65bf39be79bd49,0xbf6f3f7f3f62bf35,0x3efcbe603eacbf18,0x3f09be893e95bf0e,0x3f42bf6abf7d3f67,0xbcc93ea13f46bf6d,0x3f7ebf7cbf3e3f04,
0x3f78bf80bf553f35,0xbeac3e16bef13f22,0x3f4ebf67bf7b3f6d,0xbf2c3f04bdc93e95,0x3f5cbf3ebe480000,0x3edbbf18bf753f7f,0x3f7dbf71bf0e3ec4,0x3d49be79bf463f62,
0x3e79bd493f0ebf35,0x3f71bf7dbf623f46,0x3f18bedb3e48bec4,0x3f3ebf5cbf7f3f75,0xbf043f2c3f7bbf80,0x3f67bf4ebe953dc9,0xbe163eac3f55bf6d,0x3f80bf78bf223ef1,
0x3f42bf51bf7f3f7b,0xbf313f1dbd493e16,0x3f5fbf6abf753f6d,0xbf093ee6be793eac,0x3f73bf7abf623f55,0xbeb83e89bedb3f04,0x3f7ebf80bf463f35,0xbe2f3d97bf183f2c,
0x3f27bf133dc9be48,0x3f39bf4abf803f7d,0x3efcbecf3e95bec4,0x3f58bf65bf783f71,0x3ea1be603ef1bf0e,0x3f6fbf77bf673f5c,0x3dfbbcc93f22bf35,0x3f7cbf7fbf4e3f3e,
0xbf353f35bf803f80,0x3f35bf3500000000,0xbf353f35bf803f80,0x3f35bf3500000000,0xbf353f35bf803f80,0x3f35bf3500000000,0xbf353f35bf803f80,0x3f35bf3500000000,
0x3f35bf3580008000,0x3f35bf353f80bf80,0x3f35bf3580008000,0x3f35bf353f80bf80,0x3f35bf3580008000,0x3f35bf353f80bf80,0x3f35bf3580008000,0x3f35bf353f80bf80,
0xbf73bf7a3f753f7b,0xbf6fbf773f713f78,0xbf7ebf803f7f3f80,0xbf7cbf7f3f7d3f80,0xbf42bf513f463f55,0xbf39bf4a3f3e3f4e,0xbf5fbf6a3f623f6d,0xbf58bf653f5c3f67,
0x3ea13e60be95be48,0x3eb83e89beacbe79,0x3dfb3cc9bdc98000,0x3e2f3d97be16bd49,0x3f273f13bf22bf0e,0x3f313f1dbf2cbf18,0x3efc3ecfbef1bec4,0x3f093ee6bf04bedb,
0xbf04bf2c3f0e3f35,0xbedbbf183ef13f22,0xbe16beac3e483ec4,0xbd49be793dc93e95,0xbf78bf803f7b3f80,0xbf71bf7d3f753f7f,0xbf4ebf673f553f6d,0xbf3ebf5c3f463f62,
0x3f5c3f3ebf55bf35,0x3f673f4ebf62bf46,0x3f7d3f71bf7bbf6d,0x3f803f78bf7fbf75,0x3e793d49be488000,0x3eac3e16be95bdc9,0x3f183edbbf0ebec4,0x3f2c3f04bf22bef1,
0x3f093e89bef1be48,0x3f273ecfbf18beac,0xbcc9bea13dc93ec4,0x3dfbbe2fbd493e79,0xbf13bf4a3f223f55,0xbee6bf313f043f3e,0xbf6fbf7f3f753f80,0xbf5fbf7a3f673f7d,
0x3f583f77bf62bf7b,0x3f423f6abf4ebf71,0x3f803f73bf7fbf6d,0x3f7e3f7cbf80bf78,0x3f513f1dbf46bf0e,0x3f653f39bf5cbf2c,0x3eb83d97be958000,0x3efc3e60bedbbe16,
0xbf62bf7f3f6d3f80,0xbf46bf753f553f7b,0xbe95bf223ec43f35,0xbdc9bef13e483f0e,0x3ef13dc9bec40000,0x3f223e95bf0ebe48,0x3f753f46bf6dbf35,0x3f7f3f62bf7bbf55,
0x3ef13dc9bec48000,0x3f223e95bf0ebe48,0x3f753f46bf6dbf35,0x3f7f3f62bf7bbf55,0x3f623f7fbf6dbf80,0x3f463f75bf55bf7b,0x3e953f22bec4bf35,0x3dc93ef1be48bf0e,
0x3cc9bee63dc93f0e,0x3e89be60be163eac,0xbf51bf7e3f623f80,0xbf27bf6f3f3e3f78,0x3f6a3f7fbf75bf7b,0x3f4a3f7cbf5cbf80,0x3f583efcbf46bec4,0x3f733f31bf67bf18,
0x3f803f65bf7fbf55,0x3f773f7abf7dbf71,0x3f133dfbbef18000,0x3f423eb8bf2cbe79,0xbecf3d973e95be48,0xbf1dbe2f3f043d49,0x3f093f5fbf22bf6d,0x3ea13f39bedbbf4e,
0x3f803f4ebf7bbf35,0x3f783f71bf7fbf62,0x3edb3f5cbf0ebf6d,0x3e163f2cbe95bf46,0xbf3ebf7d3f553f80,0xbf04bf673f223f75,0x3eacbe79be483ec4,0x3f183d49bef13dc9,
0x3d493f18be48bf35,0xbe793eac3dc9bef1,0xbf67bf043f553ec4,0xbf7dbf3e3f753f22,0x3f2c3e16bf0e8000,0x3f5c3edbbf46be95,0x3f713f78bf7bbf6d,0x3f4e3f80bf62bf7f,
0xbe893ecf3dc9bf0e,0xbf133d973edbbe79,0x3f653f7abf75bf6d,0x3f313f7ebf4ebf80,0x3f1dbcc9bef13e48,0x3f583ea1bf3ebe16,0xbf27bf7c3f463f80,0xbeb8bf5f3f043f71,
0xbf77bf6a3f7f3f55,0xbf51bf7f3f673f78,0xbee63e603e95bec4,0xbf39bdfb3f18bd49,0x3f4a3f80bf62bf7b,0x3f093f73bf2cbf7d,0x3f423e2fbf228000,0x3f6f3efcbf5cbeac,
0xbf0ebf7b3f353f80,0xbe48bf553ec43f6d,0x3f553e48bf350000,0x3f7b3f0ebf6dbec4,0x3f0e3f7bbf35bf80,0x3e483f55bec4bf6d,0xbf55be483f350000,0xbf7bbf0e3f6d3ec4,
0x3f553e48bf358000,0x3f7b3f0ebf6dbec4,0x3f0e3f7bbf35bf80,0x3e483f55bec4bf6d,0xbf55be483f358000,0xbf7bbf0e3f6d3ec4,0xbf0ebf7b3f353f80,0xbe48bf553ec43f6d,
0x3f773ecfbf62be48,0x3f7c3f42bf80bf18,0xbee6bf7a3f223f80,0xbcc9bf4a3e793f67,0xbf7ebf393f7f3f0e,0xbf58bf733f713f5c,0x3d973f51be95bf6d,0xbeb83efc3e16bf2c,
0x3e893f6abef1bf7b,0xbe2f3f27bd49bf4e,0x3f653e60bf468000,0x3f803f1dbf78bedb,0x3dfbbf313dc93f55,0x3f09bea1beac3f04,0xbf7fbf133f753ec4,0xbf6fbf5f3f7d3f3e,
0xbedb3f043e48bf35,0xbf4e3d493f22be95,0xbf2cbf7d3f553f6d,0xbe79bf713ef13f7f,0xbeacbf783f0e3f80,0x3e16bf3e3dc93f62,0x3f803f18bf7bbec4,0x3f5c3f67bf75bf46,
0xbf67bf5c3f7b3f35,0xbf18bf803f463f75,0x3f3ebe16bf0e3ec4,0x3f783eacbf62bdc9,0x3f713e79bf558000,0x3f7d3f2cbf7fbef1,0xbd493f4ebe48bf6d,0xbf043edb3e95bf22,
0xbcc9bf653e953f7b,0x3efcbf09be793f3e,0xbf513dfb3f22bec4,0xbf7fbecf3f713e16,0x3f6f3f42bf7fbf0e,0x3f1d3f7cbf4ebf67,0xbe60bf773ef13f80,0x3ea1bf31bd493f5c,
0x3f803ee6bf75be48,0x3f5f3f58bf78bf2c,0xbf13bf7e3f463f6d,0xbd97bf6a3eac3f7d,0xbeb83f273dc9bf55,0xbf4a3e2f3f18bedb,0x3f7a3e89bf628000,0x3f733f39bf80bf04,
0xbdc9bf753ec43f80,0x3ef1bf22be483f55,0x3f463f62bf6dbf35,0x3e953f7fbf0ebf7b,0xbf7fbe953f6d0000,0xbf62bf463f7b3f0e,0x3f22bef1bec43f35,0x3f753dc9bf553e48,
0x3f7f3e95bf6d8000,0x3f623f46bf7bbf0e,0xbf223ef13ec4bf35,0xbf75bdc93f55be48,0xbdc9bf753ec43f80,0x3ef1bf22be483f55,0x3f463f62bf6dbf35,0x3e953f7fbf0ebf7b,
0x3f093f77bf46bf55,0xbd973f6fbe79bf80,0x3cc9bf733e953f80,0x3f1dbf13beac3f4e,0x3f7c3dfbbf623e48,0x3f653f31bf7dbedb,0xbf6abf273f7f3ec4,0xbefcbf7a3f3e3f5c,
0xbf583e893f22bf0e,0xbf7fbeb83f783d49,0x3f803ea1bf758000,0x3f4a3f51bf71bf18,0x3e2f3f7ebef1bf7b,0xbee63f393e16bf67,0x3ecfbf42bdc93f6d,0x3f5fbe60bf2c3f04,
0xbf18bf673f553f35,0x3d49bf783e953f7f,0x3f5c3f2cbf7bbec4,0x3eac3f7dbf22bf62,0x3e16bf713e483f80,0x3f3ebf04bef13f46,0x3e793f80bf0ebf6d,0xbedb3f4e3dc9bf75,
0x3f4ebedbbf0e3f35,0x3f803e79bf753dc9,0xbf043f3e3e48bf6d,0xbf713e163f46bef1,0x3f7d3eacbf7b8000,0x3f2c3f5cbf62bf22,0xbf783d493f55bec4,0xbf67bf183f7f3e95,
0x3ea13f7abf22bf55,0xbecf3f5f3d49bf7d,0xbdfbbf803ef13f6d,0x3f13bf42be793f71,0xbd973f7cbe95bf7b,0xbf393f1d3edbbf5c,0x3e89bf6f3dc93f80,0x3f58bee6bf183f3e,
0xbf733e603f46bf0e,0xbf6abefc3f803e16,0x3f7ebcc9bf623ec4,0x3f513f27bf78beac,0xbf7fbe2f3f75be48,0xbf31bf4a3f673f04,0x3f773eb8bf7f8000,0x3f093f65bf4ebf2c,
0x3ec4bf6d00003f80,0x3f6dbec4bf353f35,0xbec43f6d0000bf80,0xbf6d3ec43f35bf35,0x3ec4bf6d00003f80,0x3f6dbec4bf353f35,0xbec43f6d0000bf80,0xbf6d3ec43f35bf35,
0x3f6d3ec4bf808000,0x3ec43f6dbf35bf35,0xbf6dbec43f808000,0xbec4bf6d3f353f35,0x3f6d3ec4bf808000,0x3ec43f6dbf35bf35,0xbf6dbec43f808000,0xbec4bf6d3f353f35,
0xbf273f513e95bf7b,0xbf803dfb3f67bf04,0x3efcbf6abdc93f80,0x3f7abea1bf4e3f2c,0xbf653f093f22bf55,0xbf6fbe893f80be16,0x3f4abf31bef13f6d,0x3f7c3d97bf783eac,
0xbf42bf133f753e48,0xbcc9bf7e3edb3f5c,0x3f5f3ecfbf7f8000,0x3e603f73bf18bf3e,0xbee6bf583f463f0e,0x3eb8bf773d493f7d,0x3f1d3f39bf62bec4,0xbe2f3f7fbe79bf71,
0x3f7dbeacbf553f35,0x3f3e3f04bf75bdc9,0xbf78bd493f7bbec4,0xbedbbf4e3f463ef1,0x3f18bf67be483f80,0x3f80be79bf623f22,0xbf5c3f2c3f0ebf6d,0xbf71be163f7fbe95,
0x3e163f71bf0ebf35,0xbf2c3f5c3e95bf7f,0x3e79bf803e483f6d,0x3f67bf18bf223f62,0x3f4e3edbbf7b8000,0x3d493f78bef1bf46,0xbf04bf3e3f553ec4,0x3eacbf7d3dc93f75,
0xbf13bf1d3f623e48,0x3ea1bf803e163f67,0x3f6f3d97bf7f3ec4,0x3e893f58bf2cbf04,0xbf7a3efc3f46bf55,0xbf42becf3f78bd49,0x3f31bf65be953f80,0x3f7ebe2fbf713f18,
0x3f51bf4abef13f7b,0x3f733cc9bf7d3edb,0xbeb83f7fbdc9bf6d,0xbf773f093f3ebf5c,0xbe60bf5f3f223f0e,0x3f27bf6abe793f80,0x3f393ee6bf758000,0xbdfb3f7cbeacbf4e,
0x3f46bf62bec43f80,0x3f75bdc9bf7b3f0e,0xbf7f3e953f6dbf35,0xbef1bf223f553e48,0x3f223ef1bf6d0000,0xbe953f7fbe48bf55,0x3dc9bf753ec43f35,0x3f62bf46bf0e3f7b,
0x3f223ef1bf6d8000,0xbe953f7fbe48bf55,0x3dc9bf753ec43f35,0x3f62bf46bf0e3f7b,0xbf463f623ec4bf80,0xbf753dc93f7bbf0e,0x3f7fbe95bf6d3f35,0x3ef13f22bf55be48,
0xbf6a3d973f7fbf0e,0xbdfbbf513f183edb,0x3f58bf5fbef13f80,0x3f65bcc9bf803f04,0x3f39bf73be953f7b,0x3f77be60bf783f2c,0x3e2f3f4abf22bec4,0xbf423f6f3eacbf7d,
0x3ecfbf7f3dc93f55,0x3f7ebf13bf4e3f67,0x3f093efcbf628000,0xbee63f80bd49bf5c,0x3f313ea1bf753e48,0xbe893f7abe79bf3e,0xbf7c3f1d3f46bf6d,0xbf27beb83f71be16,
0xbeac3f78be48bf35,0xbf7d3f2c3f46bf75,0x3f80bf18bf553f6d,0x3f043edbbf623dc9,0x3f67bf5cbf0e3f80,0x3f4e3d49bf7f3ef1,0xbf3ebe163f7bbec4,0x3e79bf713e953f22,
0xbf713e793f7bbf35,0xbe16bf3e3f223e95,0x3d493f4ebf0ebec4,0xbf5c3f673ef1bf7f,0x3edb3f04bf558000,0xbf183f803dc9bf62,0x3f2cbf7dbe483f6d,0x3f78beacbf753f46,
0x3f4abcc9bf7f3f0e,0xbe603f65beacbf04,0xbf423f7c3e95bf6d,0xbf6a3e893f7dbf3e,0xbefcbeb83f62be48,0x3f13bf7fbd493f4e,0x3f73bf58bf223f80,0x3f313dfbbf783edb,
0xbf1d3f803dc9bf55,0xbf7a3ee63f71bf5c,0xbf27be2f3f75bec4,0x3ecfbf773e163f2c,0x3f5fbf6fbef13f7b,0x3f51bd97bf803f18,0x3ea13f09bf468000,0xbf393f7e3e79bf67,
0x3f7bbf55bf353f80,0x3f0e3e48bf6d3ec4,0xbe48bf0e3f350000,0x3f55bf7bbec43f6d,0xbf7b3f553f35bf80,0xbf0ebe483f6dbec4,0x3e483f0ebf350000,0xbf553f7b3ec4bf6d,
0x3e483f0ebf358000,0xbf553f7b3ec4bf6d,0x3f7bbf55bf353f80,0x3f0e3e48bf6d3ec4,0xbe48bf0e3f358000,0x3f55bf7bbec43f6d,0xbf7b3f553f35bf80,0xbf0ebe483f6dbec4,
0x3dfbbf393ef13e48,0x3f7abf65bf2c3f7d,0x3f7fbf51bf463f80,0x3ecf3e89bf5c3eac,0xbefc3f6fbdc9bf0e,0xbf7c3f273f67bf78,0xbf733f093f75bf6d,0xbcc9bf1d3f183d49,
0x3f7ebf31bf623f7b,0x3e603ee6bf3e3e16,0x3d973f13bf228000,0xbf6a3f773f04bf71,0xbf5f3eb83f7fbf55,0x3e2fbf423edb3e79,0x3ea1bf583e953ec4,0x3f80bf4abf4e3f80,
0xbf2c3e163f7bbf35,0x3f04bf673dc93ef1,0xbf713f783f0ebf6d,0xbf183d493f75bf22,0x3f80bf4ebf553f80,0x3e793eacbf463e95,0x3edbbf5c3e483ec4,0x3f7dbf3ebf623f7f,
0x3f3ebf7dbe483f35,0x3f5cbedbbf7f3f62,0xbeacbe793f55bec4,0x3f4ebf80be953f46,0xbd493f18bf0e8000,0xbf783f713f22bf75,0x3f67bf04bf7b3f6d,0xbe163f2cbef1bdc9,
0xbf6f3f273f75bf7b,0x3dfbbf133f04bd49,0xbe60be893f46bec4,0x3f65bf80bedb3f4e,0x3f31bf73bdc93f0e,0x3f5fbf09bf7d3f71,0x3f7cbf4abf623f80,0x3d973ecfbf2c3e79,
0x3eb8bf423e953e48,0x3f7ebf51bf5c3f80,0x3f7abf77bf223f6d,0x3ee63cc9bf673f18,0x3f39bea1bf7f3f55,0xbefc3f58be16beac,0xbe2f3f1dbef18000,0xbf7f3f6a3f3ebf78,
0x3f75bf46bf6d3f80,0xbdc93ef1bf0e3e48,0x3f62bf7fbec43f35,0x3f22be95bf7b3f55,0x3e95bf223ec40000,0x3f7fbf62bf553f7b,0xbef13dc93f6dbf35,0x3f46bf75be483f0e,
0xbe953f22bec48000,0xbf7f3f623f55bf7b,0x3ef1bdc9bf6d3f35,0xbf463f753e48bf0e,0x3f75bf46bf6d3f80,0xbdc93ef1bf0e3e48,0x3f62bf7fbec43f35,0x3f22be95bf7b3f55,
0x3f7cbf7ebf223f55,0x3ea1bcc9bf5c3f2c,0x3f6abf42bf753f80,0xbe893f09bedb3e16,0x3e60befc3ef1be48,0x3f7fbf6fbf4e3f71,0x3f39bf65bdc93ec4,0x3f4abf13bf803f78,
0x3e2f3dfbbf463f0e,0xbf733f803f04bf3e,0xbecf3f27be958000,0xbf773f583f67bf7d,0x3f7abf5fbf623f7b,0xbd973eb8bf183eac,0x3f31bee6bf7f3f6d,0xbf1d3f51bd49be79,
0x3f78bf80bf0e3f35,0x3eacbe16bf623f46,0x3f4ebf67be483ec4,0x3f2cbf04bf7f3f75,0x3f5cbf3ebf7b3f80,0xbedb3f18be953dc9,0x3f7dbf71bf553f6d,0xbd493e79bf223ef1,
0x3e79bd49bf553f35,0xbf713f7d3ef1bf22,0x3f18bedbbf7b3f6d,0xbf3e3f5c3dc9be95,0xbf043f2cbe488000,0xbf673f4e3f75bf7f,0xbe163eacbf0e3ec4,0xbf803f783f46bf62,
0x3f7fbf7cbf463f55,0xbcc93dfbbf2c3f18,0x3f77bf6fbf623f6d,0xbe603ea1bf043edb,0x3f65bf58bf753f7b,0xbecf3efcbeac3e79,0x3f4abf39bf7f3f80,0xbf133f27be163d49,
0xbd973e2fbf223f0e,0xbf803f7e3f3ebf4e,0xbe893eb8bef13ec4,0xbf7a3f733f5cbf67,0xbee63f09be953e48,0xbf6a3f5f3f71bf78,0xbf1d3f31bdc98000,0xbf513f423f7dbf80,
0xbf353f35bf803f80,0x3f35bf3500000000,0xbf353f35bf803f80,0x3f35bf3500000000,0xbf353f35bf803f80,0x3f35bf3500000000,0xbf353f35bf803f80,0x3f35bf3500000000,
0x3f35bf3580008000,0x3f35bf353f80bf80,0x3f35bf3580008000,0x3f35bf353f80bf80,0x3f35bf3580008000,0x3f35bf353f80bf80,0x3f35bf3580008000,0x3f35bf353f80bf80,
0xbee6bf093ef13f0e,0xbecfbefc3edb3f04,0xbf1dbf313f223f35,0xbf13bf273f183f2c,0xbd97be2f3dc93e48,0xbcc9bdfb3d493e16,0xbe89beb83e953ec4,0xbe60bea13e793eac,
0x3f653f58bf62bf55,0x3f6a3f5fbf67bf5c,0x3f4a3f39bf46bf35,0x3f513f42bf4ebf3e,0x3f7f3f7cbf7fbf7b,0x3f803f7ebf80bf7d,0x3f773f6fbf75bf6d,0x3f7a3f73bf78bf71,
0x3f5c3f3ebf55bf35,0x3f673f4ebf62bf46,0x3f7d3f71bf7bbf6d,0x3f803f78bf7fbf75,0x3e793d49be480000,0x3eac3e16be95bdc9,0x3f183edbbf0ebec4,0x3f2c3f04bf22bef1,
0x3f043f2cbf0ebf35,0x3edb3f18bef1bf22,0x3e163eacbe48bec4,0x3d493e79bdc9be95,0x3f783f80bf7bbf80,0x3f713f7dbf75bf7f,0x3f4e3f67bf55bf6d,0x3f3e3f5cbf46bf62,
0x3e603efcbe95bf0e,0x3d973eb8be16bedb,0x3f393f65bf46bf6d,0x3f1d3f51bf2cbf5c,0x3f7c3f7ebf7fbf7b,0x3f733f80bf78bf80,0x3f6a3f42bf62bf35,0x3f773f58bf71bf4e,
0xbf7abf5f3f753f55,0xbf7fbf6f3f7d3f67,0xbf31bee63f223ec4,0xbf4abf133f3e3f04,0xbe2f3dfb3dc9be48,0xbea1bcc93e79bd49,0x3ecf3f27bef1bf35,0x3e893f09beacbf18,
0x3f623f7fbf6dbf80,0x3f463f75bf55bf7b,0x3e953f22bec4bf35,0x3dc93ef1be48bf0e,0xbef1bdc93ec40000,0xbf22be953f0e3e48,0xbf75bf463f6d3f35,0xbf7fbf623f7b3f55,
0xbef1bdc93ec48000,0xbf22be953f0e3e48,0xbf75bf463f6d3f35,0xbf7fbf623f7b3f55,0xbf62bf7f3f6d3f80,0xbf46bf753f553f7b,0xbe95bf223ec43f35,0xbdc9bef13e483f0e,
0xbf39bea13f223e48,0xbf5fbf093f4e3edb,0x3e2f3f1dbe95bf35,0xbd973ecfbd49bf04,0xbeb8bf423ef13f55,0xbdfbbf133e793f2c,0xbf7abf773f7f3f6d,0xbf65bf803f713f7d,
0xbf31bf733f463f7b,0xbefcbf583f183f67,0xbf7cbf4a3f753f35,0xbf7fbf6a3f803f5c,0x3f6f3f27bf62bf0e,0x3f7e3f51bf78bf3e,0x3e60be89bdc93ec4,0x3ee6bcc9beac3e16,
0xbd49bf183e483f35,0x3e79beacbdc93ef1,0x3f673f04bf55bec4,0x3f7d3f3ebf75bf22,0xbf2cbe163f0e0000,0xbf5cbedb3f463e95,0xbf71bf783f7b3f6d,0xbf4ebf803f623f7f,
0x3f803f4ebf7bbf35,0x3f783f71bf7fbf62,0x3edb3f5cbf0ebf6d,0x3e163f2cbe95bf46,0xbf3ebf7d3f553f80,0xbf04bf673f223f75,0x3eacbe79be483ec4,0x3f183d49bef13dc9,
0x3efc3f6fbf22bf7b,0x3e2f3f42beacbf5c,0x3f733f09bf62bec4,0x3f803f4abf7dbf2c,0xbdfbbf393e953f55,0x3e60bee6bd493f18,0xbf7fbf513f7f3f35,0xbf6abf773f783f67,
0xbf5fbeb83f463e48,0xbf7cbf273f713f04,0x3ea13f58bef1bf6d,0xbcc93f1dbe16bf3e,0x3f7e3f31bf75bf0e,0x3f7a3f65bf80bf4e,0x3d97bf133dc93f35,0x3ecfbe89be793edb,
0xbf0ebf7b3f353f80,0xbe48bf553ec43f6d,0x3f553e48bf350000,0x3f7b3f0ebf6dbec4,0x3f0e3f7bbf35bf80,0x3e483f55bec4bf6d,0xbf55be483f350000,0xbf7bbf0e3f6d3ec4,
0x3f553e48bf358000,0x3f7b3f0ebf6dbec4,0x3f0e3f7bbf35bf80,0x3e483f55bec4bf6d,0xbf55be483f358000,0xbf7bbf0e3f6d3ec4,0xbf0ebf7b3f353f80,0xbe48bf553ec43f6d,
0x3f5f3f6fbf75bf55,0x3f133f7fbf3ebf7d,0x3ea1bf09bdc93f35,0x3f31bdfbbf043eac,0xbf1dbf803f463f7b,0xbe60bf653edb3f78,0xbf273e2f3ef1bec4,0xbf6abe893f4e3d49,
0xbefc3eb83e95bf0e,0xbf51bd973f2cbe16,0x3f733f58bf7fbf35,0x3f393f7ebf5cbf71,0x3f4a3cc9bf223e48,0x3f7a3ee6bf67be79,0xbf42bf7c3f623f6d,0xbecfbf773f183f80,
0xbf67bf5c3f7b3f35,0xbf18bf803f463f75,0x3f3ebe16bf0e3ec4,0x3f783eacbf62bdc9,0x3f713e79bf550000,0x3f7d3f2cbf7fbef1,0xbd493f4ebe48bf6d,0xbf043edb3e95bf22,
0x3edbbf04be483f35,0x3f4ebd49bf223e95,0x3f2c3f7dbf55bf6d,0x3e793f71bef1bf7f,0x3eac3f78bf0ebf80,0xbe163f3ebdc9bf62,0xbf80bf183f7b3ec4,0xbf5cbf673f753f46,
0x3f393f73bf62bf55,0x3e893f7abf04bf80,0x3e2fbf4a3dc93f6d,0x3f27beb8bedb3f18,0xbf6abd973f46be48,0xbf7ebf133f7d3eac,0x3f583f5fbf75bf35,0x3ee63f80bf2cbf78,
0xbf313ea13ef1bf0e,0xbf77be603f5cbd49,0x3f7c3f1dbf7fbec4,0x3f423f6fbf67bf4e,0xbecfbf7f3f223f7b,0x3dfbbf513e163f71,0xbf093efc3e95bf35,0xbf65bcc93f3ebe79,
0x3dc93f75bec4bf80,0xbef13f223e48bf55,0xbf46bf623f6d3f35,0xbe95bf7f3f0e3f7b,0x3f7f3e95bf6d0000,0x3f623f46bf7bbf0e,0xbf223ef13ec4bf35,0xbf75bdc93f55be48,
0xbf7fbe953f6d8000,0xbf62bf463f7b3f0e,0x3f22bef1bec43f35,0x3f753dc9bf553e48,0x3dc93f75bec4bf80,0xbef13f223e48bf55,0xbf46bf623f6d3f35,0xbe95bf7f3f0e3f7b,
0x3e60bf5f3dc93f7b,0x3f42becfbf043f2c,0xbf393ee63ef1bf35,0xbf7ebe2f3f67be16,0xbf51bf4a3f753f0e,0xbea1bf803f183f71,0x3eb83f7fbf22bf6d,0xbe893f58bd49bf78,
0x3f7a3efcbf7fbe48,0x3f273f6abf5cbf3e,0xbf31bf653f623f35,0xbdfbbf7c3edb3f7d,0x3f13bf1dbe953f55,0x3f73bcc9bf4e3eac,0xbf6f3d973f46bec4,0xbf77bf093f803e79,
0xbf4e3edb3f0ebf35,0xbf80be793f75bdc9,0x3f04bf3ebe483f6d,0x3f71be16bf463ef1,0xbf7dbeac3f7b0000,0xbf2cbf5c3f623f22,0x3f78bd49bf553ec4,0x3f673f18bf7fbe95,
0xbf18bf673f553f35,0x3d49bf783e953f7f,0x3f5c3f2cbf7bbec4,0x3eac3f7dbf22bf62,0x3e16bf713e483f80,0x3f3ebf04bef13f46,0x3e793f80bf0ebf6d,0xbedb3f4e3dc9bf75,
0x3f653f09bf7fbe48,0x3eb83f77bf2cbf4e,0xbf4abf313f753ec4,0xbe2fbf7f3f043f67,0x3f273f51bf62bf0e,0xbcc93f7ebeacbf78,0xbefcbf6a3f463f35,0x3e60bf733e163f80,
0xbee63f583dc9bf7b,0xbf6f3e893f3ebf18,0x3f1dbf39be953f6d,0x3f7cbd97bf5c3edb,0xbf423f133ef1bf55,0xbf80bdfb3f71be79,0x3f5fbecfbf223f35,0x3f7a3ea1bf7d3d49,
0x3ec4bf6d00003f80,0x3f6dbec4bf353f35,0xbec43f6d0000bf80,0xbf6d3ec43f35bf35,0x3ec4bf6d00003f80,0x3f6dbec4bf353f35,0xbec43f6d0000bf80,0xbf6d3ec43f35bf35,
0x3f6d3ec4bf808000,0x3ec43f6dbf35bf35,0xbf6dbec43f808000,0xbec4bf6d3f353f35,0x3f6d3ec4bf808000,0x3ec43f6dbf35bf35,0xbf6dbec43f808000,0xbec4bf6d3f353f35,
0xbf7f3e2f3f62bf0e,0xbf39bf1d3f713e79,0x3f77beb8bf463f35,0x3f583ee6bf7dbd49,0xbf73be603f7fbe48,0xbecfbf5f3f3e3f18,0x3f7e3cc9bf753ec4,0x3f133f42bf5cbedb,
0xbd97bf7c3ef13f55,0x3f31bf4abeac3f78,0x3e893f6fbf22bf35,0xbf093f653e16bf80,0x3ea1bf7a3dc93f7b,0x3f6abefcbf2c3f4e,0xbdfb3f80be95bf6d,0xbf513f273f04bf67,
0x3e163f71bf0ebf35,0xbf2c3f5c3e95bf7f,0x3e79bf803e483f6d,0x3f67bf18bf223f62,0x3f4e3edbbf7b0000,0x3d493f78bef1bf46,0xbf04bf3e3f553ec4,0x3eacbf7d3dc93f75,
0xbf7d3eac3f55bf35,0xbf3ebf043f753dc9,0x3f783d49bf7b3ec4,0x3edb3f4ebf46bef1,0xbf183f673e48bf80,0xbf803e793f62bf22,0x3f5cbf2cbf0e3f6d,0x3f713e16bf7f3e95,
0x3f7cbdfbbf753f0e,0x3ee63f39bf4ebeac,0xbf6a3f273f22bf6d,0xbf5fbe603f80be79,0x3f09bf77bdc93f7b,0x3f7fbeb8bf5c3f3e,0x3cc93f73bef1bf35,0xbf4a3f513edbbf7d,
0xbe2f3f7ebe95bf55,0xbf653f313f18bf71,0xbecfbf423f463ec4,0x3efcbf7abd493f78,0x3f583e89bf7f3e48,0x3d973f6fbf04bf2c,0xbf803ea13f62bf35,0xbf1dbf133f673e16,
0xbf463f623ec4bf80,0xbf753dc93f7bbf0e,0x3f7fbe95bf6d3f35,0x3ef13f22bf55be48,0xbf22bef13f6d0000,0x3e95bf7f3e483f55,0xbdc93f75bec4bf35,0xbf623f463f0ebf7b,
0xbf22bef13f6d8000,0x3e95bf7f3e483f55,0xbdc93f75bec4bf35,0xbf623f463f0ebf7b,0x3f46bf62bec43f80,0x3f75bdc9bf7b3f0e,0xbf7f3e953f6dbf35,0xbef1bf223f553e48,
0x3eb83f27bf46be48,0xbf1d3f7c3e16bf71,0xbf7a3e893f75bf35,0xbea1bf313f3e3e79,0xbf803ee63f62bf55,0xbefcbf093f5c3d49,0x3f13bf7ebdc93f6d,0x3f7fbecfbf673f4e,
0xbf6f3f423f22bf7b,0xbf4abe2f3f7dbeac,0x3e60bf773e953f35,0x3f73bf39bf2c3f78,0x3cc9bf653ef13f0e,0x3f5fbf58bf043f80,0x3f513dfbbf7f3ec4,0xbd973f6abedbbf18,
0x3f71be79bf7b3f35,0x3e163f3ebf22be95,0xbd49bf4e3f0e3ec4,0x3f5cbf67bef13f7f,0xbedbbf043f550000,0x3f18bf80bdc93f62,0xbf2c3f7d3e48bf6d,0xbf783eac3f75bf46,
0xbeac3f78be48bf35,0xbf7d3f2c3f46bf75,0x3f80bf18bf553f6d,0x3f043edbbf623dc9,0x3f67bf5cbf0e3f80,0x3f4e3d49bf7f3ef1,0xbf3ebe163f7bbec4,0x3e79bf713e953f22,
0x3f7ebf39bf463f7b,0x3f093ea1bf673e79,0xbd973f51bef1bec4,0xbf6f3f5f3f18bf80,0xbf773ecf3f75bf55,0xbe2fbf273f2c3e16,0x3ee6bf7a3dc93f35,0x3f80bf1dbf5c3f71,
0x3dfb3f31bf22be48,0xbf583f733edbbf78,0xbf7f3f133f62bf6d,0xbeb8befc3f4ebd49,0x3e89bf6a3e953f0e,0x3f7cbf42bf3e3f7d,0x3f65be60bf7f3f35,0xbcc93f4abf04beac,
0x3f7bbf55bf353f80,0x3f0e3e48bf6d3ec4,0xbe48bf0e3f350000,0x3f55bf7bbec43f6d,0xbf7b3f553f35bf80,0xbf0ebe483f6dbec4,0x3e483f0ebf350000,0xbf553f7b3ec4bf6d,
0x3e483f0ebf358000,0xbf553f7b3ec4bf6d,0x3f7bbf55bf353f80,0x3f0e3e48bf6d3ec4,0xbe48bf0e3f358000,0x3f55bf7bbec43f6d,0xbf7b3f553f35bf80,0xbf0ebe483f6dbec4,
0x3f4abf80be953f55,0x3f58bea1bf803f4e,0x3f42be2fbf7f3f35,0xbeb83f5fbe79bedb,0xbf773f6a3f22bf7b,0xbf13bd973f71bf04,0xbee6be603f62bec4,0x3f31bf7ebe163f3e,
0x3f1d3cc9bf753f0e,0xbf093f73bd49bf18,0xbf273f7c3dc9bf35,0xbf6f3efc3f78bf67,0xbe89becf3f46be48,0x3f51bf7fbeac3f5c,0x3f65bf7abef13f6d,0x3f39bdfbbf7d3f2c,
0x3f3ebf7dbe483f35,0x3f5cbedbbf7f3f62,0xbeacbe793f55bec4,0x3f4ebf80be953f46,0xbd493f18bf0e0000,0xbf783f713f22bf75,0x3f67bf04bf7b3f6d,0xbe163f2cbef1bdc9,
0x3f2cbe16bf7b3f35,0xbf043f67bdc9bef1,0x3f71bf78bf0e3f6d,0x3f18bd49bf753f22,0xbf803f4e3f55bf80,0xbe79beac3f46be95,0xbedb3f5cbe48bec4,0xbf7d3f3e3f62bf7f,
0x3f6abf7fbef13f55,0x3f1dbe2fbf783f3e,0x3f58befcbf7f3f6d,0xbea13f39beacbe16,0x3cc93ee6bf223e48,0xbf773f7a3f18bf67,0xbf513f7e3e95bf35,0xbf423eb83f80bf5c,
0x3ecf3d97bf623f0e,0xbf4a3f7c3e79bf2c,0xbf093f5fbdc9bec4,0xbf733f313f71bf7d,0xbf803f653f46bf7b,0xbe89be603f4ebedb,0xbf133dfb3f75bf35,0x3f27bf6fbd493f04,
0xbf753f463f6dbf80,0x3dc9bef13f0ebe48,0xbf623f7f3ec4bf35,0xbf223e953f7bbf55,0xbe953f22bec40000,0xbf7f3f623f55bf7b,0x3ef1bdc9bf6d3f35,0xbf463f753e48bf0e,
0x3e95bf223ec48000,0x3f7fbf62bf553f7b,0xbef13dc93f6dbf35,0x3f46bf75be483f0e,0xbf753f463f6dbf80,0x3dc9bef13f0ebe48,0xbf623f7f3ec4bf35,0xbf223e953f7bbf55,
0xbf513f1d3f7fbf7b,0x3ee6bf313e793d49,0xbeb83d973f62bf35,0x3f5fbf7abeac3f18,0xbf583f773e95bf0e,0xbf273ecf3f7dbf67,0xbf803f733f46bf6d,0xbdfbbe2f3f3ebf04,
0x3f13bf4a3dc93e48,0x3f65bf39bf783f80,0x3f6fbf7fbef13f35,0x3efcbe60bf713f4e,0xbf093e893f75bf55,0x3f42bf6abe163edb,0x3cc9bea13f22bec4,0x3f7ebf7cbf2c3f5c,
0xbe793d493f55bf35,0x3f71bf7dbef13f22,0xbf183edb3f7bbf6d,0x3f3ebf5cbdc93e95,0x3f04bf2c3e480000,0x3f67bf4ebf753f7f,0x3e16beac3f0ebec4,0x3f80bf78bf463f62,
0x3f78bf80bf0e3f35,0x3eacbe16bf623f46,0x3f4ebf67be483ec4,0x3f2cbf04bf7f3f75,0x3f5cbf3ebf7b3f80,0xbedb3f18be953dc9,0x3f7dbf71bf553f6d,0xbd493e79bf223ef1,
0x3f42bf51bdc93e48,0x3f31bf1dbf803f7d,0x3f5fbf6abe953ec4,0x3f09bee6bf783f71,0x3f73bf7abef13f0e,0x3eb8be89bf673f5c,0x3f7ebf80bf223f35,0x3e2fbd97bf4e3f3e,
0x3f27bf13bf7f3f7b,0xbf393f4a3d49be16,0x3efcbecfbf753f6d,0xbf583f653e79beac,0x3ea1be60bf623f55,0xbf6f3f773edbbf04,0x3dfbbcc9bf463f35,0xbf7c3f7f3f18bf2c,
0xbf353f35bf803f80,0x3f35bf3500000000,0xbf353f35bf803f80,0x3f35bf3500000000,0xbf353f35bf803f80,0x3f35bf3500000000,0xbf353f35bf803f80,0x3f35bf3500000000,
0x3f35bf3580008000,0x3f35bf353f80bf80,0x3f35bf3580008000,0x3f35bf353f80bf80,0x3f35bf3580008000,0x3f35bf353f80bf80,0x3f35bf3580008000,0x3f35bf353f80bf80,
0x3ea13e60be95be48,0x3eb83e89beacbe79,0x3dfb3cc9bdc90000,0x3e2f3d97be16bd49,0x3f273f13bf22bf0e,0x3f313f1dbf2cbf18,0x3efc3ecfbef1bec4,0x3f093ee6bf04bedb,
0x3f733f7abf75bf7b,0x3f6f3f77bf71bf78,0x3f7e3f80bf7fbf80,0x3f7c3f7fbf7dbf80,0x3f423f51bf46bf55,0x3f393f4abf3ebf4e,0x3f5f3f6abf62bf6d,0x3f583f65bf5cbf67,
0x3f043f2cbf0ebf35,0x3edb3f18bef1bf22,0x3e163eacbe48bec4,0x3d493e79bdc9be95,0x3f783f80bf7bbf80,0x3f713f7dbf75bf7f,0x3f4e3f67bf55bf6d,0x3f3e3f5cbf46bf62,
0xbf5cbf3e3f553f35,0xbf67bf4e3f623f46,0xbf7dbf713f7b3f6d,0xbf80bf783f7f3f75,0xbe79bd493e488000,0xbeacbe163e953dc9,0xbf18bedb3f0e3ec4,0xbf2cbf043f223ef1,
0xbf58bf773f623f7b,0xbf42bf6a3f4e3f71,0xbf80bf733f7f3f6d,0xbf7ebf7c3f803f78,0xbf51bf1d3f463f0e,0xbf65bf393f5c3f2c,0xbeb8bd973e950000,0xbefcbe603edb3e16,
0x3f093e89bef1be48,0x3f273ecfbf18beac,0xbcc9bea13dc93ec4,0x3dfbbe2fbd493e79,0xbf13bf4a3f223f55,0xbee6bf313f043f3e,0xbf6fbf7f3f753f80,0xbf5fbf7a3f673f7d,
0xbf62bf7f3f6d3f80,0xbf46bf753f553f7b,0xbe95bf223ec43f35,0xbdc9bef13e483f0e,0x3ef13dc9bec40000,0x3f223e95bf0ebe48,0x3f753f46bf6dbf35,0x3f7f3f62bf7bbf55,
0x3ef13dc9bec48000,0x3f223e95bf0ebe48,0x3f753f46bf6dbf35,0x3f7f3f62bf7bbf55,0x3f623f7fbf6dbf80,0x3f463f75bf55bf7b,0x3e953f22bec4bf35,0x3dc93ef1be48bf0e,
0x3f803f65bf7fbf55,0x3f773f7abf7dbf71,0x3f133dfbbef10000,0x3f423eb8bf2cbe79,0xbecf3d973e95be48,0xbf1dbe2f3f043d49,0x3f093f5fbf22bf6d,0x3ea13f39bedbbf4e,
0xbcc93ee6bdc9bf0e,0xbe893e603e16beac,0x3f513f7ebf62bf80,0x3f273f6fbf3ebf78,0xbf6abf7f3f753f7b,0xbf4abf7c3f5c3f80,0xbf58befc3f463ec4,0xbf73bf313f673f18,
0xbf80bf4e3f7b3f35,0xbf78bf713f7f3f62,0xbedbbf5c3f0e3f6d,0xbe16bf2c3e953f46,0x3f3e3f7dbf55bf80,0x3f043f67bf22bf75,0xbeac3e793e48bec4,0xbf18bd493ef1bdc9,
0xbd49bf183e483f35,0x3e79beacbdc93ef1,0x3f673f04bf55bec4,0x3f7d3f3ebf75bf22,0xbf2cbe163f0e8000,0xbf5cbedb3f463e95,0xbf71bf783f7b3f6d,0xbf4ebf803f623f7f,
0x3f773f6abf7fbf55,0x3f513f7fbf67bf78,0x3ee6be60be953ec4,0x3f393dfbbf183d49,0xbf4abf803f623f7b,0xbf09bf733f2c3f7d,0xbf42be2f3f220000,0xbf6fbefc3f5c3eac,
0xbe893ecf3dc9bf0e,0xbf133d973edbbe79,0x3f653f7abf75bf6d,0x3f313f7ebf4ebf80,0x3f1dbcc9bef13e48,0x3f583ea1bf3ebe16,0xbf27bf7c3f463f80,0xbeb8bf5f3f043f71,
0xbf0ebf7b3f353f80,0xbe48bf553ec43f6d,0x3f553e48bf350000,0x3f7b3f0ebf6dbec4,0x3f0e3f7bbf35bf80,0x3e483f55bec4bf6d,0xbf55be483f350000,0xbf7bbf0e3f6d3ec4,
0x3f553e48bf358000,0x3f7b3f0ebf6dbec4,0x3f0e3f7bbf35bf80,0x3e483f55bec4bf6d,0xbf55be483f358000,0xbf7bbf0e3f6d3ec4,0xbf0ebf7b3f353f80,0xbe48bf553ec43f6d,
0x3e893f6abef1bf7b,0xbe2f3f27bd49bf4e,0x3f653e60bf460000,0x3f803f1dbf78bedb,0x3dfbbf313dc93f55,0x3f09bea1beac3f04,0xbf7fbf133f753ec4,0xbf6fbf5f3f7d3f3e,
0xbf77becf3f623e48,0xbf7cbf423f803f18,0x3ee63f7abf22bf80,0x3cc93f4abe79bf67,0x3f7e3f39bf7fbf0e,0x3f583f73bf71bf5c,0xbd97bf513e953f6d,0x3eb8befcbe163f2c,
0x3edbbf04be483f35,0x3f4ebd49bf223e95,0x3f2c3f7dbf55bf6d,0x3e793f71bef1bf7f,0x3eac3f78bf0ebf80,0xbe163f3ebdc9bf62,0xbf80bf183f7b3ec4,0xbf5cbf673f753f46,
0x3f673f5cbf7bbf35,0x3f183f80bf46bf75,0xbf3e3e163f0ebec4,0xbf78beac3f623dc9,0xbf71be793f558000,0xbf7dbf2c3f7f3ef1,0x3d49bf4e3e483f6d,0x3f04bedbbe953f22,
0xbf80bee63f753e48,0xbf5fbf583f783f2c,0x3f133f7ebf46bf6d,0x3d973f6abeacbf7d,0x3eb8bf27bdc93f55,0x3f4abe2fbf183edb,0xbf7abe893f620000,0xbf73bf393f803f04,
0xbcc9bf653e953f7b,0x3efcbf09be793f3e,0xbf513dfb3f22bec4,0xbf7fbecf3f713e16,0x3f6f3f42bf7fbf0e,0x3f1d3f7cbf4ebf67,0xbe60bf773ef13f80,0x3ea1bf31bd493f5c,
0xbdc9bf753ec43f80,0x3ef1bf22be483f55,0x3f463f62bf6dbf35,0x3e953f7fbf0ebf7b,0xbf7fbe953f6d0000,0xbf62bf463f7b3f0e,0x3f22bef1bec43f35,0x3f753dc9bf553e48,
0x3f7f3e95bf6d8000,0x3f623f46bf7bbf0e,0xbf223ef13ec4bf35,0xbf75bdc93f55be48,0xbdc9bf753ec43f80,0x3ef1bf22be483f55,0x3f463f62bf6dbf35,0x3e953f7fbf0ebf7b,
0xbf583e893f22bf0e,0xbf7fbeb83f783d49,0x3f803ea1bf750000,0x3f4a3f51bf71bf18,0x3e2f3f7ebef1bf7b,0xbee63f393e16bf67,0x3ecfbf42bdc93f6d,0x3f5fbe60bf2c3f04,
0xbf09bf773f463f55,0x3d97bf6f3e793f80,0xbcc93f73be95bf80,0xbf1d3f133eacbf4e,0xbf7cbdfb3f62be48,0xbf65bf313f7d3edb,0x3f6a3f27bf7fbec4,0x3efc3f7abf3ebf5c,
0x3f183f67bf55bf35,0xbd493f78be95bf7f,0xbf5cbf2c3f7b3ec4,0xbeacbf7d3f223f62,0xbe163f71be48bf80,0xbf3e3f043ef1bf46,0xbe79bf803f0e3f6d,0x3edbbf4ebdc93f75,
0xbf4e3edb3f0ebf35,0xbf80be793f75bdc9,0x3f04bf3ebe483f6d,0x3f71be16bf463ef1,0xbf7dbeac3f7b8000,0xbf2cbf5c3f623f22,0x3f78bd49bf553ec4,0x3f673f18bf7fbe95,
0x3f73be60bf463f0e,0x3f6a3efcbf80be16,0xbf7e3cc93f62bec4,0xbf51bf273f783eac,0x3f7f3e2fbf753e48,0x3f313f4abf67bf04,0xbf77beb83f7f0000,0xbf09bf653f4e3f2c,
0x3ea13f7abf22bf55,0xbecf3f5f3d49bf7d,0xbdfbbf803ef13f6d,0x3f13bf42be793f71,0xbd973f7cbe95bf7b,0xbf393f1d3edbbf5c,0x3e89bf6f3dc93f80,0x3f58bee6bf183f3e,
0x3ec4bf6d00003f80,0x3f6dbec4bf353f35,0xbec43f6d0000bf80,0xbf6d3ec43f35bf35,0x3ec4bf6d00003f80,0x3f6dbec4bf353f35,0xbec43f6d0000bf80,0xbf6d3ec43f35bf35,
0x3f6d3ec4bf808000,0x3ec43f6dbf35bf35,0xbf6dbec43f808000,0xbec4bf6d3f353f35,0x3f6d3ec4bf808000,0x3ec43f6dbf35bf35,0xbf6dbec43f808000,0xbec4bf6d3f353f35,
0xbf42bf133f753e48,0xbcc9bf7e3edb3f5c,0x3f5f3ecfbf7f0000,0x3e603f73bf18bf3e,0xbee6bf583f463f0e,0x3eb8bf773d493f7d,0x3f1d3f39bf62bec4,0xbe2f3f7fbe79bf71,
0x3f27bf51be953f7b,0x3f80bdfbbf673f04,0xbefc3f6a3dc9bf80,0xbf7a3ea13f4ebf2c,0x3f65bf09bf223f55,0x3f6f3e89bf803e16,0xbf4a3f313ef1bf6d,0xbf7cbd973f78beac,
0xbf7d3eac3f55bf35,0xbf3ebf043f753dc9,0x3f783d49bf7b3ec4,0x3edb3f4ebf46bef1,0xbf183f673e48bf80,0xbf803e793f62bf22,0x3f5cbf2cbf0e3f6d,0x3f713e16bf7f3e95,
0xbe16bf713f0e3f35,0x3f2cbf5cbe953f7f,0xbe793f80be48bf6d,0xbf673f183f22bf62,0xbf4ebedb3f7b8000,0xbd49bf783ef13f46,0x3f043f3ebf55bec4,0xbeac3f7dbdc9bf75,
0xbf513f4a3ef1bf7b,0xbf73bcc93f7dbedb,0x3eb8bf7f3dc93f6d,0x3f77bf09bf3e3f5c,0x3e603f5fbf22bf0e,0xbf273f6a3e79bf80,0xbf39bee63f750000,0x3dfbbf7c3eac3f4e,
0xbf13bf1d3f623e48,0x3ea1bf803e163f67,0x3f6f3d97bf7f3ec4,0x3e893f58bf2cbf04,0xbf7a3efc3f46bf55,0xbf42becf3f78bd49,0x3f31bf65be953f80,0x3f7ebe2fbf713f18,
0x3f46bf62bec43f80,0x3f75bdc9bf7b3f0e,0xbf7f3e953f6dbf35,0xbef1bf223f553e48,0x3f223ef1bf6d0000,0xbe953f7fbe48bf55,0x3dc9bf753ec43f35,0x3f62bf46bf0e3f7b,
0x3f223ef1bf6d8000,0xbe953f7fbe48bf55,0x3dc9bf753ec43f35,0x3f62bf46bf0e3f7b,0xbf463f623ec4bf80,0xbf753dc93f7bbf0e,0x3f7fbe95bf6d3f35,0x3ef13f22bf55be48,
0x3ecfbf7f3dc93f55,0x3f7ebf13bf4e3f67,0x3f093efcbf620000,0xbee63f80bd49bf5c,0x3f313ea1bf753e48,0xbe893f7abe79bf3e,0xbf7c3f1d3f46bf6d,0xbf27beb83f71be16,
0x3f6abd97bf7f3f0e,0x3dfb3f51bf18bedb,0xbf583f5f3ef1bf80,0xbf653cc93f80bf04,0xbf393f733e95bf7b,0xbf773e603f78bf2c,0xbe2fbf4a3f223ec4,0x3f42bf6fbeac3f7d,
0x3eacbf783e483f35,0x3f7dbf2cbf463f75,0xbf803f183f55bf6d,0xbf04bedb3f62bdc9,0xbf673f5c3f0ebf80,0xbf4ebd493f7fbef1,0x3f3e3e16bf7b3ec4,0xbe793f71be95bf22,
0x3f71be79bf7b3f35,0x3e163f3ebf22be95,0xbd49bf4e3f0e3ec4,0x3f5cbf67bef13f7f,0xbedbbf043f558000,0x3f18bf80bdc93f62,0xbf2c3f7d3e48bf6d,0xbf783eac3f75bf46,
0x3f1dbf80bdc93f55,0x3f7abee6bf713f5c,0x3f273e2fbf753ec4,0xbecf3f77be16bf2c,0xbf5f3f6f3ef1bf7b,0xbf513d973f80bf18,0xbea1bf093f460000,0x3f39bf7ebe793f67,
0x3f4abcc9bf7f3f0e,0xbe603f65beacbf04,0xbf423f7c3e95bf6d,0xbf6a3e893f7dbf3e,0xbefcbeb83f62be48,0x3f13bf7fbd493f4e,0x3f73bf58bf223f80,0x3f313dfbbf783edb,
0x3f7bbf55bf353f80,0x3f0e3e48bf6d3ec4,0xbe48bf0e3f350000,0x3f55bf7bbec43f6d,0xbf7b3f553f35bf80,0xbf0ebe483f6dbec4,0x3e483f0ebf350000,0xbf553f7b3ec4bf6d,
0x3e483f0ebf358000,0xbf553f7b3ec4bf6d,0x3f7bbf55bf353f80,0x3f0e3e48bf6d3ec4,0xbe48bf0e3f358000,0x3f55bf7bbec43f6d,0xbf7b3f553f35bf80,0xbf0ebe483f6dbec4,
0x3f7ebf31bf623f7b,0x3e603ee6bf3e3e16,0x3d973f13bf220000,0xbf6a3f773f04bf71,0xbf5f3eb83f7fbf55,0x3e2fbf423edb3e79,0x3ea1bf583e953ec4,0x3f80bf4abf4e3f80,
0xbdfb3f39bef1be48,0xbf7a3f653f2cbf7d,0xbf7f3f513f46bf80,0xbecfbe893f5cbeac,0x3efcbf6f3dc93f0e,0x3f7cbf27bf673f78,0x3f73bf09bf753f6d,0x3cc93f1dbf18bd49,
0x3f2cbe16bf7b3f35,0xbf043f67bdc9bef1,0x3f71bf78bf0e3f6d,0x3f18bd49bf753f22,0xbf803f4e3f55bf80,0xbe79beac3f46be95,0xbedb3f5cbe48bec4,0xbf7d3f3e3f62bf7f,
0xbf3e3f7d3e48bf35,0xbf5c3edb3f7fbf62,0x3eac3e79bf553ec4,0xbf4e3f803e95bf46,0x3d49bf183f0e8000,0x3f78bf71bf223f75,0xbf673f043f7bbf6d,0x3e16bf2c3ef13dc9,
0xbeb83f42be95be48,0xbf7e3f513f5cbf80,0xbf7a3f773f22bf6d,0xbee6bcc93f67bf18,0xbf393ea13f7fbf55,0x3efcbf583e163eac,0x3e2fbf1d3ef10000,0x3f7fbf6abf3e3f78,
0xbf6f3f273f75bf7b,0x3dfbbf133f04bd49,0xbe60be893f46bec4,0x3f65bf80bedb3f4e,0x3f31bf73bdc93f0e,0x3f5fbf09bf7d3f71,0x3f7cbf4abf623f80,0x3d973ecfbf2c3e79,
0x3f75bf46bf6d3f80,0xbdc93ef1bf0e3e48,0x3f62bf7fbec43f35,0x3f22be95bf7b3f55,0x3e95bf223ec40000,0x3f7fbf62bf553f7b,0xbef13dc93f6dbf35,0x3f46bf75be483f0e,
0xbe953f22bec48000,0xbf7f3f623f55bf7b,0x3ef1bdc9bf6d3f35,0xbf463f753e48bf0e,0x3f75bf46bf6d3f80,0xbdc93ef1bf0e3e48,0x3f62bf7fbec43f35,0x3f22be95bf7b3f55,
0x3e2f3dfbbf463f0e,0xbf733f803f04bf3e,0xbecf3f27be950000,0xbf773f583f67bf7d,0x3f7abf5fbf623f7b,0xbd973eb8bf183eac,0x3f31bee6bf7f3f6d,0xbf1d3f51bd49be79,
0xbf7c3f7e3f22bf55,0xbea13cc93f5cbf2c,0xbf6a3f423f75bf80,0x3e89bf093edbbe16,0xbe603efcbef13e48,0xbf7f3f6f3f4ebf71,0xbf393f653dc9bec4,0xbf4a3f133f80bf78,
0xbf783f803f0ebf35,0xbeac3e163f62bf46,0xbf4e3f673e48bec4,0xbf2c3f043f7fbf75,0xbf5c3f3e3f7bbf80,0x3edbbf183e95bdc9,0xbf7d3f713f55bf6d,0x3d49be793f22bef1,
0xbe793d493f55bf35,0x3f71bf7dbef13f22,0xbf183edb3f7bbf6d,0x3f3ebf5cbdc93e95,0x3f04bf2c3e488000,0x3f67bf4ebf753f7f,0x3e16beac3f0ebec4,0x3f80bf78bf463f62,
0x3d97be2f3f22bf0e,0x3f80bf7ebf3e3f4e,0x3e89beb83ef1bec4,0x3f7abf73bf5c3f67,0x3ee6bf093e95be48,0x3f6abf5fbf713f78,0x3f1dbf313dc90000,0x3f51bf42bf7d3f80,
0x3f7fbf7cbf463f55,0xbcc93dfbbf2c3f18,0x3f77bf6fbf623f6d,0xbe603ea1bf043edb,0x3f65bf58bf753f7b,0xbecf3efcbeac3e79,0x3f4abf39bf7f3f80,0xbf133f27be163d49,
0xbf353f35bf803f80,0x3f35bf3500000000,0xbf353f35bf803f80,0x3f35bf3500000000,0xbf353f35bf803f80,0x3f35bf3500000000,0xbf353f35bf803f80,0x3f35bf3500000000,
0x3f35bf3580008000,0x3f35bf353f80bf80,0x3f35bf3580008000,0x3f35bf353f80bf80,0x3f35bf3580008000,0x3f35bf353f80bf80,0x3f35bf3580008000,0x3f35bf353f80bf80,
0x3f653f58bf62bf55,0x3f6a3f5fbf67bf5c,0x3f4a3f39bf46bf35,0x3f513f42bf4ebf3e,0x3f7f3f7cbf7fbf7b,0x3f803f7ebf80bf7d,0x3f773f6fbf75bf6d,0x3f7a3f73bf78bf71,
0x3ee63f09bef1bf0e,0x3ecf3efcbedbbf04,0x3f1d3f31bf22bf35,0x3f133f27bf18bf2c,0x3d973e2fbdc9be48,0x3cc93dfbbd49be16,0x3e893eb8be95bec4,0x3e603ea1be79beac,
0xbf5cbf3e3f553f35,0xbf67bf4e3f623f46,0xbf7dbf713f7b3f6d,0xbf80bf783f7f3f75,0xbe79bd493e480000,0xbeacbe163e953dc9,0xbf18bedb3f0e3ec4,0xbf2cbf043f223ef1,
0xbf04bf2c3f0e3f35,0xbedbbf183ef13f22,0xbe16beac3e483ec4,0xbd49be793dc93e95,0xbf78bf803f7b3f80,0xbf71bf7d3f753f7f,0xbf4ebf673f553f6d,0xbf3ebf5c3f463f62,
0x3f7a3f5fbf75bf55,0x3f7f3f6fbf7dbf67,0x3f313ee6bf22bec4,0x3f4a3f13bf3ebf04,0x3e2fbdfbbdc93e48,0x3ea13cc9be793d49,0xbecfbf273ef13f35,0xbe89bf093eac3f18,
0x3e603efcbe95bf0e,0x3d973eb8be16bedb,0x3f393f65bf46bf6d,0x3f1d3f51bf2cbf5c,0x3f7c3f7ebf7fbf7b,0x3f733f80bf78bf80,0x3f6a3f42bf62bf35,0x3f773f58bf71bf4e,
0x3f623f7fbf6dbf80,0x3f463f75bf55bf7b,0x3e953f22bec4bf35,0x3dc93ef1be48bf0e,0xbef1bdc93ec40000,0xbf22be953f0e3e48,0xbf75bf463f6d3f35,0xbf7fbf623f7b3f55,
0xbef1bdc93ec48000,0xbf22be953f0e3e48,0xbf75bf463f6d3f35,0xbf7fbf623f7b3f55,0xbf62bf7f3f6d3f80,0xbf46bf753f553f7b,0xbe95bf223ec43f35,0xbdc9bef13e483f0e,
0xbf31bf733f463f7b,0xbefcbf583f183f67,0xbf7cbf4a3f753f35,0xbf7fbf6a3f803f5c,0x3f6f3f27bf62bf0e,0x3f7e3f51bf78bf3e,0x3e60be89bdc93ec4,0x3ee6bcc9beac3e16,
0x3f393ea1bf22be48,0x3f5f3f09bf4ebedb,0xbe2fbf1d3e953f35,0x3d97becf3d493f04,0x3eb83f42bef1bf55,0x3dfb3f13be79bf2c,0x3f7a3f77bf7fbf6d,0x3f653f80bf71bf7d,
0x3d493f18be48bf35,0xbe793eac3dc9bef1,0xbf67bf043f553ec4,0xbf7dbf3e3f753f22,0x3f2c3e16bf0e0000,0x3f5c3edbbf46be95,0x3f713f78bf7bbf6d,0x3f4e3f80bf62bf7f,
0xbf80bf4e3f7b3f35,0xbf78bf713f7f3f62,0xbedbbf5c3f0e3f6d,0xbe16bf2c3e953f46,0x3f3e3f7dbf55bf80,0x3f043f67bf22bf75,0xbeac3e793e48bec4,0xbf18bd493ef1bdc9,
0x3f5f3eb8bf46be48,0x3f7c3f27bf71bf04,0xbea1bf583ef13f6d,0x3cc9bf1d3e163f3e,0xbf7ebf313f753f0e,0xbf7abf653f803f4e,0xbd973f13bdc9bf35,0xbecf3e893e79bedb,
0x3efc3f6fbf22bf7b,0x3e2f3f42beacbf5c,0x3f733f09bf62bec4,0x3f803f4abf7dbf2c,0xbdfbbf393e953f55,0x3e60bee6bd493f18,0xbf7fbf513f7f3f35,0xbf6abf773f783f67,
0xbf0ebf7b3f353f80,0xbe48bf553ec43f6d,0x3f553e48bf350000,0x3f7b3f0ebf6dbec4,0x3f0e3f7bbf35bf80,0x3e483f55bec4bf6d,0xbf55be483f350000,0xbf7bbf0e3f6d3ec4,
0x3f553e48bf358000,0x3f7b3f0ebf6dbec4,0x3f0e3f7bbf35bf80,0x3e483f55bec4bf6d,0xbf55be483f358000,0xbf7bbf0e3f6d3ec4,0xbf0ebf7b3f353f80,0xbe48bf553ec43f6d,
0xbefc3eb83e95bf0e,0xbf51bd973f2cbe16,0x3f733f58bf7fbf35,0x3f393f7ebf5cbf71,0x3f4a3cc9bf223e48,0x3f7a3ee6bf67be79,0xbf42bf7c3f623f6d,0xbecfbf773f183f80,
0xbf5fbf6f3f753f55,0xbf13bf7f3f3e3f7d,0xbea13f093dc9bf35,0xbf313dfb3f04beac,0x3f1d3f80bf46bf7b,0x3e603f65bedbbf78,0x3f27be2fbef13ec4,0x3f6a3e89bf4ebd49,
0x3f673f5cbf7bbf35,0x3f183f80bf46bf75,0xbf3e3e163f0ebec4,0xbf78beac3f623dc9,0xbf71be793f550000,0xbf7dbf2c3f7f3ef1,0x3d49bf4e3e483f6d,0x3f04bedbbe953f22,
0xbedb3f043e48bf35,0xbf4e3d493f22be95,0xbf2cbf7d3f553f6d,0xbe79bf713ef13f7f,0xbeacbf783f0e3f80,0x3e16bf3e3dc93f62,0x3f803f18bf7bbec4,0x3f5c3f67bf75bf46,
0x3f31bea1bef13f0e,0x3f773e60bf5c3d49,0xbf7cbf1d3f7f3ec4,0xbf42bf6f3f673f4e,0x3ecf3f7fbf22bf7b,0xbdfb3f51be16bf71,0x3f09befcbe953f35,0x3f653cc9bf3e3e79,
0x3f393f73bf62bf55,0x3e893f7abf04bf80,0x3e2fbf4a3dc93f6d,0x3f27beb8bedb3f18,0xbf6abd973f46be48,0xbf7ebf133f7d3eac,0x3f583f5fbf75bf35,0x3ee63f80bf2cbf78,
0x3dc93f75bec4bf80,0xbef13f223e48bf55,0xbf46bf623f6d3f35,0xbe95bf7f3f0e3f7b,0x3f7f3e95bf6d0000,0x3f623f46bf7bbf0e,0xbf223ef13ec4bf35,0xbf75bdc93f55be48,
0xbf7fbe953f6d8000,0xbf62bf463f7b3f0e,0x3f22bef1bec43f35,0x3f753dc9bf553e48,0x3dc93f75bec4bf80,0xbef13f223e48bf55,0xbf46bf623f6d3f35,0xbe95bf7f3f0e3f7b,
0x3f7a3efcbf7fbe48,0x3f273f6abf5cbf3e,0xbf31bf653f623f35,0xbdfbbf7c3edb3f7d,0x3f13bf1dbe953f55,0x3f73bcc9bf4e3eac,0xbf6f3d973f46bec4,0xbf77bf093f803e79,
0xbe603f5fbdc9bf7b,0xbf423ecf3f04bf2c,0x3f39bee6bef13f35,0x3f7e3e2fbf673e16,0x3f513f4abf75bf0e,0x3ea13f80bf18bf71,0xbeb8bf7f3f223f6d,0x3e89bf583d493f78,
0x3f4ebedbbf0e3f35,0x3f803e79bf753dc9,0xbf043f3e3e48bf6d,0xbf713e163f46bef1,0x3f7d3eacbf7b0000,0x3f2c3f5cbf62bf22,0xbf783d493f55bec4,0xbf67bf183f7f3e95,
0x3f183f67bf55bf35,0xbd493f78be95bf7f,0xbf5cbf2c3f7b3ec4,0xbeacbf7d3f223f62,0xbe163f71be48bf80,0xbf3e3f043ef1bf46,0xbe79bf803f0e3f6d,0x3edbbf4ebdc93f75,
0x3ee6bf58bdc93f7b,0x3f6fbe89bf3e3f18,0xbf1d3f393e95bf6d,0xbf7c3d973f5cbedb,0x3f42bf13bef13f55,0x3f803dfbbf713e79,0xbf5f3ecf3f22bf35,0xbf7abea13f7dbd49,
0x3f653f09bf7fbe48,0x3eb83f77bf2cbf4e,0xbf4abf313f753ec4,0xbe2fbf7f3f043f67,0x3f273f51bf62bf0e,0xbcc93f7ebeacbf78,0xbefcbf6a3f463f35,0x3e60bf733e163f80,
0x3ec4bf6d00003f80,0x3f6dbec4bf353f35,0xbec43f6d0000bf80,0xbf6d3ec43f35bf35,0x3ec4bf6d00003f80,0x3f6dbec4bf353f35,0xbec43f6d0000bf80,0xbf6d3ec43f35bf35,
0x3f6d3ec4bf808000,0x3ec43f6dbf35bf35,0xbf6dbec43f808000,0xbec4bf6d3f353f35,0x3f6d3ec4bf808000,0x3ec43f6dbf35bf35,0xbf6dbec43f808000,0xbec4bf6d3f353f35,
0xbd97bf7c3ef13f55,0x3f31bf4abeac3f78,0x3e893f6fbf22bf35,0xbf093f653e16bf80,0x3ea1bf7a3dc93f7b,0x3f6abefcbf2c3f4e,0xbdfb3f80be95bf6d,0xbf513f273f04bf67,
0x3f7fbe2fbf623f0e,0x3f393f1dbf71be79,0xbf773eb83f46bf35,0xbf58bee63f7d3d49,0x3f733e60bf7f3e48,0x3ecf3f5fbf3ebf18,0xbf7ebcc93f75bec4,0xbf13bf423f5c3edb,
0xbe16bf713f0e3f35,0x3f2cbf5cbe953f7f,0xbe793f80be48bf6d,0xbf673f183f22bf62,0xbf4ebedb3f7b0000,0xbd49bf783ef13f46,0x3f043f3ebf55bec4,0xbeac3f7dbdc9bf75,
0x3f7dbeacbf553f35,0x3f3e3f04bf75bdc9,0xbf78bd493f7bbec4,0xbedbbf4e3f463ef1,0x3f18bf67be483f80,0x3f80be79bf623f22,0xbf5c3f2c3f0ebf6d,0xbf71be163f7fbe95,
0x3e2fbf7e3e953f55,0x3f65bf31bf183f71,0x3ecf3f42bf46bec4,0xbefc3f7a3d49bf78,0xbf58be893f7fbe48,0xbd97bf6f3f043f2c,0x3f80bea1bf623f35,0x3f1d3f13bf67be16,
0x3f7cbdfbbf753f0e,0x3ee63f39bf4ebeac,0xbf6a3f273f22bf6d,0xbf5fbe603f80be79,0x3f09bf77bdc93f7b,0x3f7fbeb8bf5c3f3e,0x3cc93f73bef1bf35,0xbf4a3f513edbbf7d,
0xbf463f623ec4bf80,0xbf753dc93f7bbf0e,0x3f7fbe95bf6d3f35,0x3ef13f22bf55be48,0xbf22bef13f6d0000,0x3e95bf7f3e483f55,0xbdc93f75bec4bf35,0xbf623f463f0ebf7b,
0xbf22bef13f6d8000,0x3e95bf7f3e483f55,0xbdc93f75bec4bf35,0xbf623f463f0ebf7b,0x3f46bf62bec43f80,0x3f75bdc9bf7b3f0e,0xbf7f3e953f6dbf35,0xbef1bf223f553e48,
0xbf6f3f423f22bf7b,0xbf4abe2f3f7dbeac,0x3e60bf773e953f35,0x3f73bf39bf2c3f78,0x3cc9bf653ef13f0e,0x3f5fbf58bf043f80,0x3f513dfbbf7f3ec4,0xbd973f6abedbbf18,
0xbeb8bf273f463e48,0x3f1dbf7cbe163f71,0x3f7abe89bf753f35,0x3ea13f31bf3ebe79,0x3f80bee6bf623f55,0x3efc3f09bf5cbd49,0xbf133f7e3dc9bf6d,0xbf7f3ecf3f67bf4e,
0xbf713e793f7bbf35,0xbe16bf3e3f223e95,0x3d493f4ebf0ebec4,0xbf5c3f673ef1bf7f,0x3edb3f04bf550000,0xbf183f803dc9bf62,0x3f2cbf7dbe483f6d,0x3f78beacbf753f46,
0x3eacbf783e483f35,0x3f7dbf2cbf463f75,0xbf803f183f55bf6d,0xbf04bedb3f62bdc9,0xbf673f5c3f0ebf80,0xbf4ebd493f7fbef1,0x3f3e3e16bf7b3ec4,0xbe793f71be95bf22,
0xbdfbbf313f223e48,0x3f58bf73bedb3f78,0x3f7fbf13bf623f6d,0x3eb83efcbf4e3d49,0xbe893f6abe95bf0e,0xbf7c3f423f3ebf7d,0xbf653e603f7fbf35,0x3cc9bf4a3f043eac,
0x3f7ebf39bf463f7b,0x3f093ea1bf673e79,0xbd973f51bef1bec4,0xbf6f3f5f3f18bf80,0xbf773ecf3f75bf55,0xbe2fbf273f2c3e16,0x3ee6bf7a3dc93f35,0x3f80bf1dbf5c3f71,
0x3f7bbf55bf353f80,0x3f0e3e48bf6d3ec4,0xbe48bf0e3f350000,0x3f55bf7bbec43f6d,0xbf7b3f553f35bf80,0xbf0ebe483f6dbec4,0x3e483f0ebf350000,0xbf553f7b3ec4bf6d,
0x3e483f0ebf358000,0xbf553f7b3ec4bf6d,0x3f7bbf55bf353f80,0x3f0e3e48bf6d3ec4,0xbe48bf0e3f358000,0x3f55bf7bbec43f6d,0xbf7b3f553f35bf80,0xbf0ebe483f6dbec4,
0x3f1d3cc9bf753f0e,0xbf093f73bd49bf18,0xbf273f7c3dc9bf35,0xbf6f3efc3f78bf67,0xbe89becf3f46be48,0x3f51bf7fbeac3f5c,0x3f65bf7abef13f6d,0x3f39bdfbbf7d3f2c,
0xbf4a3f803e95bf55,0xbf583ea13f80bf4e,0xbf423e2f3f7fbf35,0x3eb8bf5f3e793edb,0x3f77bf6abf223f7b,0x3f133d97bf713f04,0x3ee63e60bf623ec4,0xbf313f7e3e16bf3e,
0xbf3e3f7d3e48bf35,0xbf5c3edb3f7fbf62,0x3eac3e79bf553ec4,0xbf4e3f803e95bf46,0x3d49bf183f0e0000,0x3f78bf71bf223f75,0xbf673f043f7bbf6d,0x3e16bf2c3ef13dc9,
0xbf2c3e163f7bbf35,0x3f04bf673dc93ef1,0xbf713f783f0ebf6d,0xbf183d493f75bf22,0x3f80bf4ebf553f80,0x3e793eacbf463e95,0x3edbbf5c3e483ec4,0x3f7dbf3ebf623f7f,
0xbecfbd973f62bf0e,0x3f4abf7cbe793f2c,0x3f09bf5f3dc93ec4,0x3f73bf31bf713f7d,0x3f80bf65bf463f7b,0x3e893e60bf4e3edb,0x3f13bdfbbf753f35,0xbf273f6f3d49bf04,
0x3f6abf7fbef13f55,0x3f1dbe2fbf783f3e,0x3f58befcbf7f3f6d,0xbea13f39beacbe16,0x3cc93ee6bf223e48,0xbf773f7a3f18bf67,0xbf513f7e3e95bf35,0xbf423eb83f80bf5c,
0xbf753f463f6dbf80,0x3dc9bef13f0ebe48,0xbf623f7f3ec4bf35,0xbf223e953f7bbf55,0xbe953f22bec40000,0xbf7f3f623f55bf7b,0x3ef1bdc9bf6d3f35,0xbf463f753e48bf0e,
0x3e95bf223ec48000,0x3f7fbf62bf553f7b,0xbef13dc93f6dbf35,0x3f46bf75be483f0e,0xbf753f463f6dbf80,0x3dc9bef13f0ebe48,0xbf623f7f3ec4bf35,0xbf223e953f7bbf55,
0x3f13bf4a3dc93e48,0x3f65bf39bf783f80,0x3f6fbf7fbef13f35,0x3efcbe60bf713f4e,0xbf093e893f75bf55,0x3f42bf6abe163edb,0x3cc9bea13f22bec4,0x3f7ebf7cbf2c3f5c,
0x3f51bf1dbf7f3f7b,0xbee63f31be79bd49,0x3eb8bd97bf623f35,0xbf5f3f7a3eacbf18,0x3f58bf77be953f0e,0x3f27becfbf7d3f67,0x3f80bf73bf463f6d,0x3dfb3e2fbf3e3f04,
0x3e79bd49bf553f35,0xbf713f7d3ef1bf22,0x3f18bedbbf7b3f6d,0xbf3e3f5c3dc9be95,0xbf043f2cbe480000,0xbf673f4e3f75bf7f,0xbe163eacbf0e3ec4,0xbf803f783f46bf62,
0xbf783f803f0ebf35,0xbeac3e163f62bf46,0xbf4e3f673e48bec4,0xbf2c3f043f7fbf75,0xbf5c3f3e3f7bbf80,0x3edbbf183e95bdc9,0xbf7d3f713f55bf6d,0x3d49be793f22bef1,
0xbf273f133f7fbf7b,0x3f39bf4abd493e16,0xbefc3ecf3f75bf6d,0x3f58bf65be793eac,0xbea13e603f62bf55,0x3f6fbf77bedb3f04,0xbdfb3cc93f46bf35,0x3f7cbf7fbf183f2c,
0x3f42bf51bdc93e48,0x3f31bf1dbf803f7d,0x3f5fbf6abe953ec4,0x3f09bee6bf783f71,0x3f73bf7abef13f0e,0x3eb8be89bf673f5c,0x3f7ebf80bf223f35,0x3e2fbd97bf4e3f3e,
0xbf353f35bf803f80,0x3f35bf3500000000,0xbf353f35bf803f80,0x3f35bf3500000000,0xbf353f35bf803f80,0x3f35bf3500000000,0xbf353f35bf803f80,0x3f35bf3500000000,
0x3f35bf3580008000,0x3f35bf353f80bf80,0x3f35bf3580008000,0x3f35bf353f80bf80,0x3f35bf3580008000,0x3f35bf353f80bf80,0x3f35bf3580008000,0x3f35bf353f80bf80,
0x3f733f7abf75bf7b,0x3f6f3f77bf71bf78,0x3f7e3f80bf7fbf80,0x3f7c3f7fbf7dbf80,0x3f423f51bf46bf55,0x3f393f4abf3ebf4e,0x3f5f3f6abf62bf6d,0x3f583f65bf5cbf67,
0xbea1be603e953e48,0xbeb8be893eac3e79,0xbdfbbcc93dc98000,0xbe2fbd973e163d49,0xbf27bf133f223f0e,0xbf31bf1d3f2c3f18,0xbefcbecf3ef13ec4,0xbf09bee63f043edb,
0xbf04bf2c3f0e3f35,0xbedbbf183ef13f22,0xbe16beac3e483ec4,0xbd49be793dc93e95,0xbf78bf803f7b3f80,0xbf71bf7d3f753f7f,0xbf4ebf673f553f6d,0xbf3ebf5c3f463f62,
0x3f5c3f3ebf55bf35,0x3f673f4ebf62bf46,0x3f7d3f71bf7bbf6d,0x3f803f78bf7fbf75,0x3e793d49be488000,0x3eac3e16be95bdc9,0x3f183edbbf0ebec4,0x3f2c3f04bf22bef1,
0xbf09be893ef13e48,0xbf27becf3f183eac,0x3cc93ea1bdc9bec4,0xbdfb3e2f3d49be79,0x3f133f4abf22bf55,0x3ee63f31bf04bf3e,0x3f6f3f7fbf75bf80,0x3f5f3f7abf67bf7d,
0xbf58bf773f623f7b,0xbf42bf6a3f4e3f71,0xbf80bf733f7f3f6d,0xbf7ebf7c3f803f78,0xbf51bf1d3f463f0e,0xbf65bf393f5c3f2c,0xbeb8bd973e958000,0xbefcbe603edb3e16,
0xbf62bf7f3f6d3f80,0xbf46bf753f553f7b,0xbe95bf223ec43f35,0xbdc9bef13e483f0e,0x3ef13dc9bec40000,0x3f223e95bf0ebe48,0x3f753f46bf6dbf35,0x3f7f3f62bf7bbf55,
0x3ef13dc9bec48000,0x3f223e95bf0ebe48,0x3f753f46bf6dbf35,0x3f7f3f62bf7bbf55,0x3f623f7fbf6dbf80,0x3f463f75bf55bf7b,0x3e953f22bec4bf35,0x3dc93ef1be48bf0e,
0xbcc93ee6bdc9bf0e,0xbe893e603e16beac,0x3f513f7ebf62bf80,0x3f273f6fbf3ebf78,0xbf6abf7f3f753f7b,0xbf4abf7c3f5c3f80,0xbf58befc3f463ec4,0xbf73bf313f673f18,
0xbf80bf653f7f3f55,0xbf77bf7a3f7d3f71,0xbf13bdfb3ef18000,0xbf42beb83f2c3e79,0x3ecfbd97be953e48,0x3f1d3e2fbf04bd49,0xbf09bf5f3f223f6d,0xbea1bf393edb3f4e,
0x3f803f4ebf7bbf35,0x3f783f71bf7fbf62,0x3edb3f5cbf0ebf6d,0x3e163f2cbe95bf46,0xbf3ebf7d3f553f80,0xbf04bf673f223f75,0x3eacbe79be483ec4,0x3f183d49bef13dc9,
0x3d493f18be48bf35,0xbe793eac3dc9bef1,0xbf67bf043f553ec4,0xbf7dbf3e3f753f22,0x3f2c3e16bf0e8000,0x3f5c3edbbf46be95,0x3f713f78bf7bbf6d,0x3f4e3f80bf62bf7f,
0x3e89becfbdc93f0e,0x3f13bd97bedb3e79,0xbf65bf7a3f753f6d,0xbf31bf7e3f4e3f80,0xbf1d3cc93ef1be48,0xbf58bea13f3e3e16,0x3f273f7cbf46bf80,0x3eb83f5fbf04bf71,
0x3f773f6abf7fbf55,0x3f513f7fbf67bf78,0x3ee6be60be953ec4,0x3f393dfbbf183d49,0xbf4abf803f623f7b,0xbf09bf733f2c3f7d,0xbf42be2f3f228000,0xbf6fbefc3f5c3eac,
0xbf0ebf7b3f353f80,0xbe48bf553ec43f6d,0x3f553e48bf350000,0x3f7b3f0ebf6dbec4,0x3f0e3f7bbf35bf80,0x3e483f55bec4bf6d,0xbf55be483f350000,0xbf7bbf0e3f6d3ec4,
0x3f553e48bf358000,0x3f7b3f0ebf6dbec4,0x3f0e3f7bbf35bf80,0x3e483f55bec4bf6d,0xbf55be483f358000,0xbf7bbf0e3f6d3ec4,0xbf0ebf7b3f353f80,0xbe48bf553ec43f6d,
0xbf77becf3f623e48,0xbf7cbf423f803f18,0x3ee63f7abf22bf80,0x3cc93f4abe79bf67,0x3f7e3f39bf7fbf0e,0x3f583f73bf71bf5c,0xbd97bf513e953f6d,0x3eb8befcbe163f2c,
0xbe89bf6a3ef13f7b,0x3e2fbf273d493f4e,0xbf65be603f468000,0xbf80bf1d3f783edb,0xbdfb3f31bdc9bf55,0xbf093ea13eacbf04,0x3f7f3f13bf75bec4,0x3f6f3f5fbf7dbf3e,
0xbedb3f043e48bf35,0xbf4e3d493f22be95,0xbf2cbf7d3f553f6d,0xbe79bf713ef13f7f,0xbeacbf783f0e3f80,0x3e16bf3e3dc93f62,0x3f803f18bf7bbec4,0x3f5c3f67bf75bf46,
0xbf67bf5c3f7b3f35,0xbf18bf803f463f75,0x3f3ebe16bf0e3ec4,0x3f783eacbf62bdc9,0x3f713e79bf558000,0x3f7d3f2cbf7fbef1,0xbd493f4ebe48bf6d,0xbf043edb3e95bf22,
0x3cc93f65be95bf7b,0xbefc3f093e79bf3e,0x3f51bdfbbf223ec4,0x3f7f3ecfbf71be16,0xbf6fbf423f7f3f0e,0xbf1dbf7c3f4e3f67,0x3e603f77bef1bf80,0xbea13f313d49bf5c,
0xbf80bee63f753e48,0xbf5fbf583f783f2c,0x3f133f7ebf46bf6d,0x3d973f6abeacbf7d,0x3eb8bf27bdc93f55,0x3f4abe2fbf183edb,0xbf7abe893f628000,0xbf73bf393f803f04,
0xbdc9bf753ec43f80,0x3ef1bf22be483f55,0x3f463f62bf6dbf35,0x3e953f7fbf0ebf7b,0xbf7fbe953f6d0000,0xbf62bf463f7b3f0e,0x3f22bef1bec43f35,0x3f753dc9bf553e48,
0x3f7f3e95bf6d8000,0x3f623f46bf7bbf0e,0xbf223ef13ec4bf35,0xbf75bdc93f55be48,0xbdc9bf753ec43f80,0x3ef1bf22be483f55,0x3f463f62bf6dbf35,0x3e953f7fbf0ebf7b,
0xbf09bf773f463f55,0x3d97bf6f3e793f80,0xbcc93f73be95bf80,0xbf1d3f133eacbf4e,0xbf7cbdfb3f62be48,0xbf65bf313f7d3edb,0x3f6a3f27bf7fbec4,0x3efc3f7abf3ebf5c,
0x3f58be89bf223f0e,0x3f7f3eb8bf78bd49,0xbf80bea13f758000,0xbf4abf513f713f18,0xbe2fbf7e3ef13f7b,0x3ee6bf39be163f67,0xbecf3f423dc9bf6d,0xbf5f3e603f2cbf04,
0xbf18bf673f553f35,0x3d49bf783e953f7f,0x3f5c3f2cbf7bbec4,0x3eac3f7dbf22bf62,0x3e16bf713e483f80,0x3f3ebf04bef13f46,0x3e793f80bf0ebf6d,0xbedb3f4e3dc9bf75,
0x3f4ebedbbf0e3f35,0x3f803e79bf753dc9,0xbf043f3e3e48bf6d,0xbf713e163f46bef1,0x3f7d3eacbf7b8000,0x3f2c3f5cbf62bf22,0xbf783d493f55bec4,0xbf67bf183f7f3e95,
0xbea1bf7a3f223f55,0x3ecfbf5fbd493f7d,0x3dfb3f80bef1bf6d,0xbf133f423e79bf71,0x3d97bf7c3e953f7b,0x3f39bf1dbedb3f5c,0xbe893f6fbdc9bf80,0xbf583ee63f18bf3e,
0x3f73be60bf463f0e,0x3f6a3efcbf80be16,0xbf7e3cc93f62bec4,0xbf51bf273f783eac,0x3f7f3e2fbf753e48,0x3f313f4abf67bf04,0xbf77beb83f7f8000,0xbf09bf653f4e3f2c,
0x3ec4bf6d00003f80,0x3f6dbec4bf353f35,0xbec43f6d0000bf80,0xbf6d3ec43f35bf35,0x3ec4bf6d00003f80,0x3f6dbec4bf353f35,0xbec43f6d0000bf80,0xbf6d3ec43f35bf35,
0x3f6d3ec4bf808000,0x3ec43f6dbf35bf35,0xbf6dbec43f808000,0xbec4bf6d3f353f35,0x3f6d3ec4bf808000,0x3ec43f6dbf35bf35,0xbf6dbec43f808000,0xbec4bf6d3f353f35,
0x3f27bf51be953f7b,0x3f80bdfbbf673f04,0xbefc3f6a3dc9bf80,0xbf7a3ea13f4ebf2c,0x3f65bf09bf223f55,0x3f6f3e89bf803e16,0xbf4a3f313ef1bf6d,0xbf7cbd973f78beac,
0x3f423f13bf75be48,0x3cc93f7ebedbbf5c,0xbf5fbecf3f7f8000,0xbe60bf733f183f3e,0x3ee63f58bf46bf0e,0xbeb83f77bd49bf7d,0xbf1dbf393f623ec4,0x3e2fbf7f3e793f71,
0x3f7dbeacbf553f35,0x3f3e3f04bf75bdc9,0xbf78bd493f7bbec4,0xbedbbf4e3f463ef1,0x3f18bf67be483f80,0x3f80be79bf623f22,0xbf5c3f2c3f0ebf6d,0xbf71be163f7fbe95,
0x3e163f71bf0ebf35,0xbf2c3f5c3e95bf7f,0x3e79bf803e483f6d,0x3f67bf18bf223f62,0x3f4e3edbbf7b8000,0x3d493f78bef1bf46,0xbf04bf3e3f553ec4,0x3eacbf7d3dc93f75,
0x3f133f1dbf62be48,0xbea13f80be16bf67,0xbf6fbd973f7fbec4,0xbe89bf583f2c3f04,0x3f7abefcbf463f55,0x3f423ecfbf783d49,0xbf313f653e95bf80,0xbf7e3e2f3f71bf18,
0xbf513f4a3ef1bf7b,0xbf73bcc93f7dbedb,0x3eb8bf7f3dc93f6d,0x3f77bf09bf3e3f5c,0x3e603f5fbf22bf0e,0xbf273f6a3e79bf80,0xbf39bee63f758000,0x3dfbbf7c3eac3f4e,
0x3f46bf62bec43f80,0x3f75bdc9bf7b3f0e,0xbf7f3e953f6dbf35,0xbef1bf223f553e48,0x3f223ef1bf6d0000,0xbe953f7fbe48bf55,0x3dc9bf753ec43f35,0x3f62bf46bf0e3f7b,
0x3f223ef1bf6d8000,0xbe953f7fbe48bf55,0x3dc9bf753ec43f35,0x3f62bf46bf0e3f7b,0xbf463f623ec4bf80,0xbf753dc93f7bbf0e,0x3f7fbe95bf6d3f35,0x3ef13f22bf55be48,
0x3f6abd97bf7f3f0e,0x3dfb3f51bf18bedb,0xbf583f5f3ef1bf80,0xbf653cc93f80bf04,0xbf393f733e95bf7b,0xbf773e603f78bf2c,0xbe2fbf4a3f223ec4,0x3f42bf6fbeac3f7d,
0xbecf3f7fbdc9bf55,0xbf7e3f133f4ebf67,0xbf09befc3f628000,0x3ee6bf803d493f5c,0xbf31bea13f75be48,0x3e89bf7a3e793f3e,0x3f7cbf1dbf463f6d,0x3f273eb8bf713e16,
0xbeac3f78be48bf35,0xbf7d3f2c3f46bf75,0x3f80bf18bf553f6d,0x3f043edbbf623dc9,0x3f67bf5cbf0e3f80,0x3f4e3d49bf7f3ef1,0xbf3ebe163f7bbec4,0x3e79bf713e953f22,
0xbf713e793f7bbf35,0xbe16bf3e3f223e95,0x3d493f4ebf0ebec4,0xbf5c3f673ef1bf7f,0x3edb3f04bf558000,0xbf183f803dc9bf62,0x3f2cbf7dbe483f6d,0x3f78beacbf753f46,
0xbf4a3cc93f7fbf0e,0x3e60bf653eac3f04,0x3f42bf7cbe953f6d,0x3f6abe89bf7d3f3e,0x3efc3eb8bf623e48,0xbf133f7f3d49bf4e,0xbf733f583f22bf80,0xbf31bdfb3f78bedb,
0x3f1dbf80bdc93f55,0x3f7abee6bf713f5c,0x3f273e2fbf753ec4,0xbecf3f77be16bf2c,0xbf5f3f6f3ef1bf7b,0xbf513d973f80bf18,0xbea1bf093f468000,0x3f39bf7ebe793f67,
0x3f7bbf55bf353f80,0x3f0e3e48bf6d3ec4,0xbe48bf0e3f350000,0x3f55bf7bbec43f6d,0xbf7b3f553f35bf80,0xbf0ebe483f6dbec4,0x3e483f0ebf350000,0xbf553f7b3ec4bf6d,
0x3e483f0ebf358000,0xbf553f7b3ec4bf6d,0x3f7bbf55bf353f80,0x3f0e3e48bf6d3ec4,0xbe48bf0e3f358000,0x3f55bf7bbec43f6d,0xbf7b3f553f35bf80,0xbf0ebe483f6dbec4,
0xbdfb3f39bef1be48,0xbf7a3f653f2cbf7d,0xbf7f3f513f46bf80,0xbecfbe893f5cbeac,0x3efcbf6f3dc93f0e,0x3f7cbf27bf673f78,0x3f73bf09bf753f6d,0x3cc93f1dbf18bd49,
0xbf7e3f313f62bf7b,0xbe60bee63f3ebe16,0xbd97bf133f228000,0x3f6abf77bf043f71,0x3f5fbeb8bf7f3f55,0xbe2f3f42bedbbe79,0xbea13f58be95bec4,0xbf803f4a3f4ebf80,
0xbf2c3e163f7bbf35,0x3f04bf673dc93ef1,0xbf713f783f0ebf6d,0xbf183d493f75bf22,0x3f80bf4ebf553f80,0x3e793eacbf463e95,0x3edbbf5c3e483ec4,0x3f7dbf3ebf623f7f,
0x3f3ebf7dbe483f35,0x3f5cbedbbf7f3f62,0xbeacbe793f55bec4,0x3f4ebf80be953f46,0xbd493f18bf0e8000,0xbf783f713f22bf75,0x3f67bf04bf7b3f6d,0xbe163f2cbef1bdc9,
0x3f6fbf27bf753f7b,0xbdfb3f13bf043d49,0x3e603e89bf463ec4,0xbf653f803edbbf4e,0xbf313f733dc9bf0e,0xbf5f3f093f7dbf71,0xbf7c3f4a3f62bf80,0xbd97becf3f2cbe79,
0xbeb83f42be95be48,0xbf7e3f513f5cbf80,0xbf7a3f773f22bf6d,0xbee6bcc93f67bf18,0xbf393ea13f7fbf55,0x3efcbf583e163eac,0x3e2fbf1d3ef18000,0x3f7fbf6abf3e3f78,
0x3f75bf46bf6d3f80,0xbdc93ef1bf0e3e48,0x3f62bf7fbec43f35,0x3f22be95bf7b3f55,0x3e95bf223ec40000,0x3f7fbf62bf553f7b,0xbef13dc93f6dbf35,0x3f46bf75be483f0e,
0xbe953f22bec48000,0xbf7f3f623f55bf7b,0x3ef1bdc9bf6d3f35,0xbf463f753e48bf0e,0x3f75bf46bf6d3f80,0xbdc93ef1bf0e3e48,0x3f62bf7fbec43f35,0x3f22be95bf7b3f55,
0xbf7c3f7e3f22bf55,0xbea13cc93f5cbf2c,0xbf6a3f423f75bf80,0x3e89bf093edbbe16,0xbe603efcbef13e48,0xbf7f3f6f3f4ebf71,0xbf393f653dc9bec4,0xbf4a3f133f80bf78,
0xbe2fbdfb3f46bf0e,0x3f73bf80bf043f3e,0x3ecfbf273e958000,0x3f77bf58bf673f7d,0xbf7a3f5f3f62bf7b,0x3d97beb83f18beac,0xbf313ee63f7fbf6d,0x3f1dbf513d493e79,
0x3f78bf80bf0e3f35,0x3eacbe16bf623f46,0x3f4ebf67be483ec4,0x3f2cbf04bf7f3f75,0x3f5cbf3ebf7b3f80,0xbedb3f18be953dc9,0x3f7dbf71bf553f6d,0xbd493e79bf223ef1,
0x3e79bd49bf553f35,0xbf713f7d3ef1bf22,0x3f18bedbbf7b3f6d,0xbf3e3f5c3dc9be95,0xbf043f2cbe488000,0xbf673f4e3f75bf7f,0xbe163eacbf0e3ec4,0xbf803f783f46bf62,
0xbf7f3f7c3f46bf55,0x3cc9bdfb3f2cbf18,0xbf773f6f3f62bf6d,0x3e60bea13f04bedb,0xbf653f583f75bf7b,0x3ecfbefc3eacbe79,0xbf4a3f393f7fbf80,0x3f13bf273e16bd49,
0x3d97be2f3f22bf0e,0x3f80bf7ebf3e3f4e,0x3e89beb83ef1bec4,0x3f7abf73bf5c3f67,0x3ee6bf093e95be48,0x3f6abf5fbf713f78,0x3f1dbf313dc98000,0x3f51bf42bf7d3f80,
0xbf353f35bf803f80,0x3f35bf3500000000,0xbf353f35bf803f80,0x3f35bf3500000000,0xbf353f35bf803f80,0x3f35bf3500000000,0xbf353f35bf803f80,0x3f35bf3500000000,
0x3f35bf3580008000,0x3f35bf353f80bf80,0x3f35bf3580008000,0x3f35bf353f80bf80,0x3f35bf3580008000,0x3f35bf353f80bf80,0x3f35bf3580008000,0x3f35bf353f80bf80,
0x3ee63f09bef1bf0e,0x3ecf3efcbedbbf04,0x3f1d3f31bf22bf35,0x3f133f27bf18bf2c,0x3d973e2fbdc9be48,0x3cc93dfbbd49be16,0x3e893eb8be95bec4,0x3e603ea1be79beac,
0xbf65bf583f623f55,0xbf6abf5f3f673f5c,0xbf4abf393f463f35,0xbf51bf423f4e3f3e,0xbf7fbf7c3f7f3f7b,0xbf80bf7e3f803f7d,0xbf77bf6f3f753f6d,0xbf7abf733f783f71,
0x3f5c3f3ebf55bf35,0x3f673f4ebf62bf46,0x3f7d3f71bf7bbf6d,0x3f803f78bf7fbf75,0x3e793d49be480000,0x3eac3e16be95bdc9,0x3f183edbbf0ebec4,0x3f2c3f04bf22bef1,
0x3f043f2cbf0ebf35,0x3edb3f18bef1bf22,0x3e163eacbe48bec4,0x3d493e79bdc9be95,0x3f783f80bf7bbf80,0x3f713f7dbf75bf7f,0x3f4e3f67bf55bf6d,0x3f3e3f5cbf46bf62,
0xbe60befc3e953f0e,0xbd97beb83e163edb,0xbf39bf653f463f6d,0xbf1dbf513f2c3f5c,0xbf7cbf7e3f7f3f7b,0xbf73bf803f783f80,0xbf6abf423f623f35,0xbf77bf583f713f4e,
0x3f7a3f5fbf75bf55,0x3f7f3f6fbf7dbf67,0x3f313ee6bf22bec4,0x3f4a3f13bf3ebf04,0x3e2fbdfbbdc93e48,0x3ea13cc9be793d49,0xbecfbf273ef13f35,0xbe89bf093eac3f18,
0x3f623f7fbf6dbf80,0x3f463f75bf55bf7b,0x3e953f22bec4bf35,0x3dc93ef1be48bf0e,0xbef1bdc93ec40000,0xbf22be953f0e3e48,0xbf75bf463f6d3f35,0xbf7fbf623f7b3f55,
0xbef1bdc93ec48000,0xbf22be953f0e3e48,0xbf75bf463f6d3f35,0xbf7fbf623f7b3f55,0xbf62bf7f3f6d3f80,0xbf46bf753f553f7b,0xbe95bf223ec43f35,0xbdc9bef13e483f0e,
0x3f393ea1bf22be48,0x3f5f3f09bf4ebedb,0xbe2fbf1d3e953f35,0x3d97becf3d493f04,0x3eb83f42bef1bf55,0x3dfb3f13be79bf2c,0x3f7a3f77bf7fbf6d,0x3f653f80bf71bf7d,
0x3f313f73bf46bf7b,0x3efc3f58bf18bf67,0x3f7c3f4abf75bf35,0x3f7f3f6abf80bf5c,0xbf6fbf273f623f0e,0xbf7ebf513f783f3e,0xbe603e893dc9bec4,0xbee63cc93eacbe16,
0xbd49bf183e483f35,0x3e79beacbdc93ef1,0x3f673f04bf55bec4,0x3f7d3f3ebf75bf22,0xbf2cbe163f0e0000,0xbf5cbedb3f463e95,0xbf71bf783f7b3f6d,0xbf4ebf803f623f7f,
0x3f803f4ebf7bbf35,0x3f783f71bf7fbf62,0x3edb3f5cbf0ebf6d,0x3e163f2cbe95bf46,0xbf3ebf7d3f553f80,0xbf04bf673f223f75,0x3eacbe79be483ec4,0x3f183d49bef13dc9,
0xbefcbf6f3f223f7b,0xbe2fbf423eac3f5c,0xbf73bf093f623ec4,0xbf80bf4a3f7d3f2c,0x3dfb3f39be95bf55,0xbe603ee63d49bf18,0x3f7f3f51bf7fbf35,0x3f6a3f77bf78bf67,
0x3f5f3eb8bf46be48,0x3f7c3f27bf71bf04,0xbea1bf583ef13f6d,0x3cc9bf1d3e163f3e,0xbf7ebf313f753f0e,0xbf7abf653f803f4e,0xbd973f13bdc9bf35,0xbecf3e893e79bedb,
0xbf0ebf7b3f353f80,0xbe48bf553ec43f6d,0x3f553e48bf350000,0x3f7b3f0ebf6dbec4,0x3f0e3f7bbf35bf80,0x3e483f55bec4bf6d,0xbf55be483f350000,0xbf7bbf0e3f6d3ec4,
0x3f553e48bf358000,0x3f7b3f0ebf6dbec4,0x3f0e3f7bbf35bf80,0x3e483f55bec4bf6d,0xbf55be483f358000,0xbf7bbf0e3f6d3ec4,0xbf0ebf7b3f353f80,0xbe48bf553ec43f6d,
0xbf5fbf6f3f753f55,0xbf13bf7f3f3e3f7d,0xbea13f093dc9bf35,0xbf313dfb3f04beac,0x3f1d3f80bf46bf7b,0x3e603f65bedbbf78,0x3f27be2fbef13ec4,0x3f6a3e89bf4ebd49,
0x3efcbeb8be953f0e,0x3f513d97bf2c3e16,0xbf73bf583f7f3f35,0xbf39bf7e3f5c3f71,0xbf4abcc93f22be48,0xbf7abee63f673e79,0x3f423f7cbf62bf6d,0x3ecf3f77bf18bf80,
0xbf67bf5c3f7b3f35,0xbf18bf803f463f75,0x3f3ebe16bf0e3ec4,0x3f783eacbf62bdc9,0x3f713e79bf550000,0x3f7d3f2cbf7fbef1,0xbd493f4ebe48bf6d,0xbf043edb3e95bf22,
0x3edbbf04be483f35,0x3f4ebd49bf223e95,0x3f2c3f7dbf55bf6d,0x3e793f71bef1bf7f,0x3eac3f78bf0ebf80,0xbe163f3ebdc9bf62,0xbf80bf183f7b3ec4,0xbf5cbf673f753f46,
0xbf39bf733f623f55,0xbe89bf7a3f043f80,0xbe2f3f4abdc9bf6d,0xbf273eb83edbbf18,0x3f6a3d97bf463e48,0x3f7e3f13bf7dbeac,0xbf58bf5f3f753f35,0xbee6bf803f2c3f78,
0x3f31bea1bef13f0e,0x3f773e60bf5c3d49,0xbf7cbf1d3f7f3ec4,0xbf42bf6f3f673f4e,0x3ecf3f7fbf22bf7b,0xbdfb3f51be16bf71,0x3f09befcbe953f35,0x3f653cc9bf3e3e79,
0x3dc93f75bec4bf80,0xbef13f223e48bf55,0xbf46bf623f6d3f35,0xbe95bf7f3f0e3f7b,0x3f7f3e95bf6d0000,0x3f623f46bf7bbf0e,0xbf223ef13ec4bf35,0xbf75bdc93f55be48,
0xbf7fbe953f6d8000,0xbf62bf463f7b3f0e,0x3f22bef1bec43f35,0x3f753dc9bf553e48,0x3dc93f75bec4bf80,0xbef13f223e48bf55,0xbf46bf623f6d3f35,0xbe95bf7f3f0e3f7b,
0xbe603f5fbdc9bf7b,0xbf423ecf3f04bf2c,0x3f39bee6bef13f35,0x3f7e3e2fbf673e16,0x3f513f4abf75bf0e,0x3ea13f80bf18bf71,0xbeb8bf7f3f223f6d,0x3e89bf583d493f78,
0xbf7abefc3f7f3e48,0xbf27bf6a3f5c3f3e,0x3f313f65bf62bf35,0x3dfb3f7cbedbbf7d,0xbf133f1d3e95bf55,0xbf733cc93f4ebeac,0x3f6fbd97bf463ec4,0x3f773f09bf80be79,
0xbf4e3edb3f0ebf35,0xbf80be793f75bdc9,0x3f04bf3ebe483f6d,0x3f71be16bf463ef1,0xbf7dbeac3f7b0000,0xbf2cbf5c3f623f22,0x3f78bd49bf553ec4,0x3f673f18bf7fbe95,
0xbf18bf673f553f35,0x3d49bf783e953f7f,0x3f5c3f2cbf7bbec4,0x3eac3f7dbf22bf62,0x3e16bf713e483f80,0x3f3ebf04bef13f46,0x3e793f80bf0ebf6d,0xbedb3f4e3dc9bf75,
0xbf65bf093f7f3e48,0xbeb8bf773f2c3f4e,0x3f4a3f31bf75bec4,0x3e2f3f7fbf04bf67,0xbf27bf513f623f0e,0x3cc9bf7e3eac3f78,0x3efc3f6abf46bf35,0xbe603f73be16bf80,
0x3ee6bf58bdc93f7b,0x3f6fbe89bf3e3f18,0xbf1d3f393e95bf6d,0xbf7c3d973f5cbedb,0x3f42bf13bef13f55,0x3f803dfbbf713e79,0xbf5f3ecf3f22bf35,0xbf7abea13f7dbd49,
0x3ec4bf6d00003f80,0x3f6dbec4bf353f35,0xbec43f6d0000bf80,0xbf6d3ec43f35bf35,0x3ec4bf6d00003f80,0x3f6dbec4bf353f35,0xbec43f6d0000bf80,0xbf6d3ec43f35bf35,
0x3f6d3ec4bf808000,0x3ec43f6dbf35bf35,0xbf6dbec43f808000,0xbec4bf6d3f353f35,0x3f6d3ec4bf808000,0x3ec43f6dbf35bf35,0xbf6dbec43f808000,0xbec4bf6d3f353f35,
0x3f7fbe2fbf623f0e,0x3f393f1dbf71be79,0xbf773eb83f46bf35,0xbf58bee63f7d3d49,0x3f733e60bf7f3e48,0x3ecf3f5fbf3ebf18,0xbf7ebcc93f75bec4,0xbf13bf423f5c3edb,
0x3d973f7cbef1bf55,0xbf313f4a3eacbf78,0xbe89bf6f3f223f35,0x3f09bf65be163f80,0xbea13f7abdc9bf7b,0xbf6a3efc3f2cbf4e,0x3dfbbf803e953f6d,0x3f51bf27bf043f67,
0x3e163f71bf0ebf35,0xbf2c3f5c3e95bf7f,0x3e79bf803e483f6d,0x3f67bf18bf223f62,0x3f4e3edbbf7b0000,0x3d493f78bef1bf46,0xbf04bf3e3f553ec4,0x3eacbf7d3dc93f75,
0xbf7d3eac3f55bf35,0xbf3ebf043f753dc9,0x3f783d49bf7b3ec4,0x3edb3f4ebf46bef1,0xbf183f673e48bf80,0xbf803e793f62bf22,0x3f5cbf2cbf0e3f6d,0x3f713e16bf7f3e95,
0xbf7c3dfb3f75bf0e,0xbee6bf393f4e3eac,0x3f6abf27bf223f6d,0x3f5f3e60bf803e79,0xbf093f773dc9bf7b,0xbf7f3eb83f5cbf3e,0xbcc9bf733ef13f35,0x3f4abf51bedb3f7d,
0x3e2fbf7e3e953f55,0x3f65bf31bf183f71,0x3ecf3f42bf46bec4,0xbefc3f7a3d49bf78,0xbf58be893f7fbe48,0xbd97bf6f3f043f2c,0x3f80bea1bf623f35,0x3f1d3f13bf67be16,
0xbf463f623ec4bf80,0xbf753dc93f7bbf0e,0x3f7fbe95bf6d3f35,0x3ef13f22bf55be48,0xbf22bef13f6d0000,0x3e95bf7f3e483f55,0xbdc93f75bec4bf35,0xbf623f463f0ebf7b,
0xbf22bef13f6d8000,0x3e95bf7f3e483f55,0xbdc93f75bec4bf35,0xbf623f463f0ebf7b,0x3f46bf62bec43f80,0x3f75bdc9bf7b3f0e,0xbf7f3e953f6dbf35,0xbef1bf223f553e48,
0xbeb8bf273f463e48,0x3f1dbf7cbe163f71,0x3f7abe89bf753f35,0x3ea13f31bf3ebe79,0x3f80bee6bf623f55,0x3efc3f09bf5cbd49,0xbf133f7e3dc9bf6d,0xbf7f3ecf3f67bf4e,
0x3f6fbf42bf223f7b,0x3f4a3e2fbf7d3eac,0xbe603f77be95bf35,0xbf733f393f2cbf78,0xbcc93f65bef1bf0e,0xbf5f3f583f04bf80,0xbf51bdfb3f7fbec4,0x3d97bf6a3edb3f18,
0x3f71be79bf7b3f35,0x3e163f3ebf22be95,0xbd49bf4e3f0e3ec4,0x3f5cbf67bef13f7f,0xbedbbf043f550000,0x3f18bf80bdc93f62,0xbf2c3f7d3e48bf6d,0xbf783eac3f75bf46,
0xbeac3f78be48bf35,0xbf7d3f2c3f46bf75,0x3f80bf18bf553f6d,0x3f043edbbf623dc9,0x3f67bf5cbf0e3f80,0x3f4e3d49bf7f3ef1,0xbf3ebe163f7bbec4,0x3e79bf713e953f22,
0xbf7e3f393f46bf7b,0xbf09bea13f67be79,0x3d97bf513ef13ec4,0x3f6fbf5fbf183f80,0x3f77becfbf753f55,0x3e2f3f27bf2cbe16,0xbee63f7abdc9bf35,0xbf803f1d3f5cbf71,
0xbdfbbf313f223e48,0x3f58bf73bedb3f78,0x3f7fbf13bf623f6d,0x3eb83efcbf4e3d49,0xbe893f6abe95bf0e,0xbf7c3f423f3ebf7d,0xbf653e603f7fbf35,0x3cc9bf4a3f043eac,
0x3f7bbf55bf353f80,0x3f0e3e48bf6d3ec4,0xbe48bf0e3f350000,0x3f55bf7bbec43f6d,0xbf7b3f553f35bf80,0xbf0ebe483f6dbec4,0x3e483f0ebf350000,0xbf553f7b3ec4bf6d,
0x3e483f0ebf358000,0xbf553f7b3ec4bf6d,0x3f7bbf55bf353f80,0x3f0e3e48bf6d3ec4,0xbe48bf0e3f358000,0x3f55bf7bbec43f6d,0xbf7b3f553f35bf80,0xbf0ebe483f6dbec4,
0xbf4a3f803e95bf55,0xbf583ea13f80bf4e,0xbf423e2f3f7fbf35,0x3eb8bf5f3e793edb,0x3f77bf6abf223f7b,0x3f133d97bf713f04,0x3ee63e60bf623ec4,0xbf313f7e3e16bf3e,
0xbf1dbcc93f75bf0e,0x3f09bf733d493f18,0x3f27bf7cbdc93f35,0x3f6fbefcbf783f67,0x3e893ecfbf463e48,0xbf513f7f3eacbf5c,0xbf653f7a3ef1bf6d,0xbf393dfb3f7dbf2c,
0x3f3ebf7dbe483f35,0x3f5cbedbbf7f3f62,0xbeacbe793f55bec4,0x3f4ebf80be953f46,0xbd493f18bf0e0000,0xbf783f713f22bf75,0x3f67bf04bf7b3f6d,0xbe163f2cbef1bdc9,
0x3f2cbe16bf7b3f35,0xbf043f67bdc9bef1,0x3f71bf78bf0e3f6d,0x3f18bd49bf753f22,0xbf803f4e3f55bf80,0xbe79beac3f46be95,0xbedb3f5cbe48bec4,0xbf7d3f3e3f62bf7f,
0xbf6a3f7f3ef1bf55,0xbf1d3e2f3f78bf3e,0xbf583efc3f7fbf6d,0x3ea1bf393eac3e16,0xbcc9bee63f22be48,0x3f77bf7abf183f67,0x3f51bf7ebe953f35,0x3f42beb8bf803f5c,
0xbecfbd973f62bf0e,0x3f4abf7cbe793f2c,0x3f09bf5f3dc93ec4,0x3f73bf31bf713f7d,0x3f80bf65bf463f7b,0x3e893e60bf4e3edb,0x3f13bdfbbf753f35,0xbf273f6f3d49bf04,
0xbf753f463f6dbf80,0x3dc9bef13f0ebe48,0xbf623f7f3ec4bf35,0xbf223e953f7bbf55,0xbe953f22bec40000,0xbf7f3f623f55bf7b,0x3ef1bdc9bf6d3f35,0xbf463f753e48bf0e,
0x3e95bf223ec48000,0x3f7fbf62bf553f7b,0xbef13dc93f6dbf35,0x3f46bf75be483f0e,0xbf753f463f6dbf80,0x3dc9bef13f0ebe48,0xbf623f7f3ec4bf35,0xbf223e953f7bbf55,
0x3f51bf1dbf7f3f7b,0xbee63f31be79bd49,0x3eb8bd97bf623f35,0xbf5f3f7a3eacbf18,0x3f58bf77be953f0e,0x3f27becfbf7d3f67,0x3f80bf73bf463f6d,0x3dfb3e2fbf3e3f04,
0xbf133f4abdc9be48,0xbf653f393f78bf80,0xbf6f3f7f3ef1bf35,0xbefc3e603f71bf4e,0x3f09be89bf753f55,0xbf423f6a3e16bedb,0xbcc93ea1bf223ec4,0xbf7e3f7c3f2cbf5c,
0xbe793d493f55bf35,0x3f71bf7dbef13f22,0xbf183edb3f7bbf6d,0x3f3ebf5cbdc93e95,0x3f04bf2c3e480000,0x3f67bf4ebf753f7f,0x3e16beac3f0ebec4,0x3f80bf78bf463f62,
0x3f78bf80bf0e3f35,0x3eacbe16bf623f46,0x3f4ebf67be483ec4,0x3f2cbf04bf7f3f75,0x3f5cbf3ebf7b3f80,0xbedb3f18be953dc9,0x3f7dbf71bf553f6d,0xbd493e79bf223ef1,
0xbf423f513dc9be48,0xbf313f1d3f80bf7d,0xbf5f3f6a3e95bec4,0xbf093ee63f78bf71,0xbf733f7a3ef1bf0e,0xbeb83e893f67bf5c,0xbf7e3f803f22bf35,0xbe2f3d973f4ebf3e,
0xbf273f133f7fbf7b,0x3f39bf4abd493e16,0xbefc3ecf3f75bf6d,0x3f58bf65be793eac,0xbea13e603f62bf55,0x3f6fbf77bedb3f04,0xbdfb3cc93f46bf35,0x3f7cbf7fbf183f2c,
0xbf353f35bf803f80,0x3f35bf3500000000,0xbf353f35bf803f80,0x3f35bf3500000000,0xbf353f35bf803f80,0x3f35bf3500000000,0xbf353f35bf803f80,0x3f35bf3500000000,
0x3f35bf3580008000,0x3f35bf353f80bf80,0x3f35bf3580008000,0x3f35bf353f80bf80,0x3f35bf3580008000,0x3f35bf353f80bf80,0x3f35bf3580008000,0x3f35bf353f80bf80,
0xbea1be603e953e48,0xbeb8be893eac3e79,0xbdfbbcc93dc90000,0xbe2fbd973e163d49,0xbf27bf133f223f0e,0xbf31bf1d3f2c3f18,0xbefcbecf3ef13ec4,0xbf09bee63f043edb,
0xbf73bf7a3f753f7b,0xbf6fbf773f713f78,0xbf7ebf803f7f3f80,0xbf7cbf7f3f7d3f80,0xbf42bf513f463f55,0xbf39bf4a3f3e3f4e,0xbf5fbf6a3f623f6d,0xbf58bf653f5c3f67,
0x3f043f2cbf0ebf35,0x3edb3f18bef1bf22,0x3e163eacbe48bec4,0x3d493e79bdc9be95,0x3f783f80bf7bbf80,0x3f713f7dbf75bf7f,0x3f4e3f67bf55bf6d,0x3f3e3f5cbf46bf62,
0xbf5cbf3e3f553f35,0xbf67bf4e3f623f46,0xbf7dbf713f7b3f6d,0xbf80bf783f7f3f75,0xbe79bd493e488000,0xbeacbe163e953dc9,0xbf18bedb3f0e3ec4,0xbf2cbf043f223ef1,
0x3f583f77bf62bf7b,0x3f423f6abf4ebf71,0x3f803f73bf7fbf6d,0x3f7e3f7cbf80bf78,0x3f513f1dbf46bf0e,0x3f653f39bf5cbf2c,0x3eb83d97be950000,0x3efc3e60bedbbe16,
0xbf09be893ef13e48,0xbf27becf3f183eac,0x3cc93ea1bdc9bec4,0xbdfb3e2f3d49be79,0x3f133f4abf22bf55,0x3ee63f31bf04bf3e,0x3f6f3f7fbf75bf80,0x3f5f3f7abf67bf7d,
0xbf62bf7f3f6d3f80,0xbf46bf753f553f7b,0xbe95bf223ec43f35,0xbdc9bef13e483f0e,0x3ef13dc9bec40000,0x3f223e95bf0ebe48,0x3f753f46bf6dbf35,0x3f7f3f62bf7bbf55,
0x3ef13dc9bec48000,0x3f223e95bf0ebe48,0x3f753f46bf6dbf35,0x3f7f3f62bf7bbf55,0x3f623f7fbf6dbf80,0x3f463f75bf55bf7b,0x3e953f22bec4bf35,0x3dc93ef1be48bf0e,
0xbf80bf653f7f3f55,0xbf77bf7a3f7d3f71,0xbf13bdfb3ef10000,0xbf42beb83f2c3e79,0x3ecfbd97be953e48,0x3f1d3e2fbf04bd49,0xbf09bf5f3f223f6d,0xbea1bf393edb3f4e,
0x3cc9bee63dc93f0e,0x3e89be60be163eac,0xbf51bf7e3f623f80,0xbf27bf6f3f3e3f78,0x3f6a3f7fbf75bf7b,0x3f4a3f7cbf5cbf80,0x3f583efcbf46bec4,0x3f733f31bf67bf18,
0xbf80bf4e3f7b3f35,0xbf78bf713f7f3f62,0xbedbbf5c3f0e3f6d,0xbe16bf2c3e953f46,0x3f3e3f7dbf55bf80,0x3f043f67bf22bf75,0xbeac3e793e48bec4,0xbf18bd493ef1bdc9,
0xbd49bf183e483f35,0x3e79beacbdc93ef1,0x3f673f04bf55bec4,0x3f7d3f3ebf75bf22,0xbf2cbe163f0e8000,0xbf5cbedb3f463e95,0xbf71bf783f7b3f6d,0xbf4ebf803f623f7f,
0xbf77bf6a3f7f3f55,0xbf51bf7f3f673f78,0xbee63e603e95bec4,0xbf39bdfb3f18bd49,0x3f4a3f80bf62bf7b,0x3f093f73bf2cbf7d,0x3f423e2fbf220000,0x3f6f3efcbf5cbeac,
0x3e89becfbdc93f0e,0x3f13bd97bedb3e79,0xbf65bf7a3f753f6d,0xbf31bf7e3f4e3f80,0xbf1d3cc93ef1be48,0xbf58bea13f3e3e16,0x3f273f7cbf46bf80,0x3eb83f5fbf04bf71,
0xbf0ebf7b3f353f80,0xbe48bf553ec43f6d,0x3f553e48bf350000,0x3f7b3f0ebf6dbec4,0x3f0e3f7bbf35bf80,0x3e483f55bec4bf6d,0xbf55be483f350000,0xbf7bbf0e3f6d3ec4,
0x3f553e48bf358000,0x3f7b3f0ebf6dbec4,0x3f0e3f7bbf35bf80,0x3e483f55bec4bf6d,0xbf55be483f358000,0xbf7bbf0e3f6d3ec4,0xbf0ebf7b3f353f80,0xbe48bf553ec43f6d,
0xbe89bf6a3ef13f7b,0x3e2fbf273d493f4e,0xbf65be603f460000,0xbf80bf1d3f783edb,0xbdfb3f31bdc9bf55,0xbf093ea13eacbf04,0x3f7f3f13bf75bec4,0x3f6f3f5fbf7dbf3e,
0x3f773ecfbf62be48,0x3f7c3f42bf80bf18,0xbee6bf7a3f223f80,0xbcc9bf4a3e793f67,0xbf7ebf393f7f3f0e,0xbf58bf733f713f5c,0x3d973f51be95bf6d,0xbeb83efc3e16bf2c,
0x3edbbf04be483f35,0x3f4ebd49bf223e95,0x3f2c3f7dbf55bf6d,0x3e793f71bef1bf7f,0x3eac3f78bf0ebf80,0xbe163f3ebdc9bf62,0xbf80bf183f7b3ec4,0xbf5cbf673f753f46,
0x3f673f5cbf7bbf35,0x3f183f80bf46bf75,0xbf3e3e163f0ebec4,0xbf78beac3f623dc9,0xbf71be793f558000,0xbf7dbf2c3f7f3ef1,0x3d49bf4e3e483f6d,0x3f04bedbbe953f22,
0x3f803ee6bf75be48,0x3f5f3f58bf78bf2c,0xbf13bf7e3f463f6d,0xbd97bf6a3eac3f7d,0xbeb83f273dc9bf55,0xbf4a3e2f3f18bedb,0x3f7a3e89bf620000,0x3f733f39bf80bf04,
0x3cc93f65be95bf7b,0xbefc3f093e79bf3e,0x3f51bdfbbf223ec4,0x3f7f3ecfbf71be16,0xbf6fbf423f7f3f0e,0xbf1dbf7c3f4e3f67,0x3e603f77bef1bf80,0xbea13f313d49bf5c,
0xbdc9bf753ec43f80,0x3ef1bf22be483f55,0x3f463f62bf6dbf35,0x3e953f7fbf0ebf7b,0xbf7fbe953f6d0000,0xbf62bf463f7b3f0e,0x3f22bef1bec43f35,0x3f753dc9bf553e48,
0x3f7f3e95bf6d8000,0x3f623f46bf7bbf0e,0xbf223ef13ec4bf35,0xbf75bdc93f55be48,0xbdc9bf753ec43f80,0x3ef1bf22be483f55,0x3f463f62bf6dbf35,0x3e953f7fbf0ebf7b,
0x3f58be89bf223f0e,0x3f7f3eb8bf78bd49,0xbf80bea13f750000,0xbf4abf513f713f18,0xbe2fbf7e3ef13f7b,0x3ee6bf39be163f67,0xbecf3f423dc9bf6d,0xbf5f3e603f2cbf04,
0x3f093f77bf46bf55,0xbd973f6fbe79bf80,0x3cc9bf733e953f80,0x3f1dbf13beac3f4e,0x3f7c3dfbbf623e48,0x3f653f31bf7dbedb,0xbf6abf273f7f3ec4,0xbefcbf7a3f3e3f5c,
0x3f183f67bf55bf35,0xbd493f78be95bf7f,0xbf5cbf2c3f7b3ec4,0xbeacbf7d3f223f62,0xbe163f71be48bf80,0xbf3e3f043ef1bf46,0xbe79bf803f0e3f6d,0x3edbbf4ebdc93f75,
0xbf4e3edb3f0ebf35,0xbf80be793f75bdc9,0x3f04bf3ebe483f6d,0x3f71be16bf463ef1,0xbf7dbeac3f7b8000,0xbf2cbf5c3f623f22,0x3f78bd49bf553ec4,0x3f673f18bf7fbe95,
0xbf733e603f46bf0e,0xbf6abefc3f803e16,0x3f7ebcc9bf623ec4,0x3f513f27bf78beac,0xbf7fbe2f3f75be48,0xbf31bf4a3f673f04,0x3f773eb8bf7f0000,0x3f093f65bf4ebf2c,
0xbea1bf7a3f223f55,0x3ecfbf5fbd493f7d,0x3dfb3f80bef1bf6d,0xbf133f423e79bf71,0x3d97bf7c3e953f7b,0x3f39bf1dbedb3f5c,0xbe893f6fbdc9bf80,0xbf583ee63f18bf3e,
0x3ec4bf6d00003f80,0x3f6dbec4bf353f35,0xbec43f6d0000bf80,0xbf6d3ec43f35bf35,0x3ec4bf6d00003f80,0x3f6dbec4bf353f35,0xbec43f6d0000bf80,0xbf6d3ec43f35bf35,
0x3f6d3ec4bf808000,0x3ec43f6dbf35bf35,0xbf6dbec43f808000,0xbec4bf6d3f353f35,0x3f6d3ec4bf808000,0x3ec43f6dbf35bf35,0xbf6dbec43f808000,0xbec4bf6d3f353f35,
0x3f423f13bf75be48,0x3cc93f7ebedbbf5c,0xbf5fbecf3f7f0000,0xbe60bf733f183f3e,0x3ee63f58bf46bf0e,0xbeb83f77bd49bf7d,0xbf1dbf393f623ec4,0x3e2fbf7f3e793f71,
0xbf273f513e95bf7b,0xbf803dfb3f67bf04,0x3efcbf6abdc93f80,0x3f7abea1bf4e3f2c,0xbf653f093f22bf55,0xbf6fbe893f80be16,0x3f4abf31bef13f6d,0x3f7c3d97bf783eac,
0xbf7d3eac3f55bf35,0xbf3ebf043f753dc9,0x3f783d49bf7b3ec4,0x3edb3f4ebf46bef1,0xbf183f673e48bf80,0xbf803e793f62bf22,0x3f5cbf2cbf0e3f6d,0x3f713e16bf7f3e95,
0xbe16bf713f0e3f35,0x3f2cbf5cbe953f7f,0xbe793f80be48bf6d,0xbf673f183f22bf62,0xbf4ebedb3f7b8000,0xbd49bf783ef13f46,0x3f043f3ebf55bec4,0xbeac3f7dbdc9bf75,
0x3f51bf4abef13f7b,0x3f733cc9bf7d3edb,0xbeb83f7fbdc9bf6d,0xbf773f093f3ebf5c,0xbe60bf5f3f223f0e,0x3f27bf6abe793f80,0x3f393ee6bf750000,0xbdfb3f7cbeacbf4e,
0x3f133f1dbf62be48,0xbea13f80be16bf67,0xbf6fbd973f7fbec4,0xbe89bf583f2c3f04,0x3f7abefcbf463f55,0x3f423ecfbf783d49,0xbf313f653e95bf80,0xbf7e3e2f3f71bf18,
0x3f46bf62bec43f80,0x3f75bdc9bf7b3f0e,0xbf7f3e953f6dbf35,0xbef1bf223f553e48,0x3f223ef1bf6d0000,0xbe953f7fbe48bf55,0x3dc9bf753ec43f35,0x3f62bf46bf0e3f7b,
0x3f223ef1bf6d8000,0xbe953f7fbe48bf55,0x3dc9bf753ec43f35,0x3f62bf46bf0e3f7b,0xbf463f623ec4bf80,0xbf753dc93f7bbf0e,0x3f7fbe95bf6d3f35,0x3ef13f22bf55be48,
0xbecf3f7fbdc9bf55,0xbf7e3f133f4ebf67,0xbf09befc3f620000,0x3ee6bf803d493f5c,0xbf31bea13f75be48,0x3e89bf7a3e793f3e,0x3f7cbf1dbf463f6d,0x3f273eb8bf713e16,
0xbf6a3d973f7fbf0e,0xbdfbbf513f183edb,0x3f58bf5fbef13f80,0x3f65bcc9bf803f04,0x3f39bf73be953f7b,0x3f77be60bf783f2c,0x3e2f3f4abf22bec4,0xbf423f6f3eacbf7d,
0x3eacbf783e483f35,0x3f7dbf2cbf463f75,0xbf803f183f55bf6d,0xbf04bedb3f62bdc9,0xbf673f5c3f0ebf80,0xbf4ebd493f7fbef1,0x3f3e3e16bf7b3ec4,0xbe793f71be95bf22,
0x3f71be79bf7b3f35,0x3e163f3ebf22be95,0xbd49bf4e3f0e3ec4,0x3f5cbf67bef13f7f,0xbedbbf043f558000,0x3f18bf80bdc93f62,0xbf2c3f7d3e48bf6d,0xbf783eac3f75bf46,
0xbf1d3f803dc9bf55,0xbf7a3ee63f71bf5c,0xbf27be2f3f75bec4,0x3ecfbf773e163f2c,0x3f5fbf6fbef13f7b,0x3f51bd97bf803f18,0x3ea13f09bf460000,0xbf393f7e3e79bf67,
0xbf4a3cc93f7fbf0e,0x3e60bf653eac3f04,0x3f42bf7cbe953f6d,0x3f6abe89bf7d3f3e,0x3efc3eb8bf623e48,0xbf133f7f3d49bf4e,0xbf733f583f22bf80,0xbf31bdfb3f78bedb,
0x3f7bbf55bf353f80,0x3f0e3e48bf6d3ec4,0xbe48bf0e3f350000,0x3f55bf7bbec43f6d,0xbf7b3f553f35bf80,0xbf0ebe483f6dbec4,0x3e483f0ebf350000,0xbf553f7b3ec4bf6d,
0x3e483f0ebf358000,0xbf553f7b3ec4bf6d,0x3f7bbf55bf353f80,0x3f0e3e48bf6d3ec4,0xbe48bf0e3f358000,0x3f55bf7bbec43f6d,0xbf7b3f553f35bf80,0xbf0ebe483f6dbec4,
0xbf7e3f313f62bf7b,0xbe60bee63f3ebe16,0xbd97bf133f220000,0x3f6abf77bf043f71,0x3f5fbeb8bf7f3f55,0xbe2f3f42bedbbe79,0xbea13f58be95bec4,0xbf803f4a3f4ebf80,
0x3dfbbf393ef13e48,0x3f7abf65bf2c3f7d,0x3f7fbf51bf463f80,0x3ecf3e89bf5c3eac,0xbefc3f6fbdc9bf0e,0xbf7c3f273f67bf78,0xbf733f093f75bf6d,0xbcc9bf1d3f183d49,
0x3f2cbe16bf7b3f35,0xbf043f67bdc9bef1,0x3f71bf78bf0e3f6d,0x3f18bd49bf753f22,0xbf803f4e3f55bf80,0xbe79beac3f46be95,0xbedb3f5cbe48bec4,0xbf7d3f3e3f62bf7f,
0xbf3e3f7d3e48bf35,0xbf5c3edb3f7fbf62,0x3eac3e79bf553ec4,0xbf4e3f803e95bf46,0x3d49bf183f0e8000,0x3f78bf71bf223f75,0xbf673f043f7bbf6d,0x3e16bf2c3ef13dc9,
0x3eb8bf423e953e48,0x3f7ebf51bf5c3f80,0x3f7abf77bf223f6d,0x3ee63cc9bf673f18,0x3f39bea1bf7f3f55,0xbefc3f58be16beac,0xbe2f3f1dbef10000,0xbf7f3f6a3f3ebf78,
0x3f6fbf27bf753f7b,0xbdfb3f13bf043d49,0x3e603e89bf463ec4,0xbf653f803edbbf4e,0xbf313f733dc9bf0e,0xbf5f3f093f7dbf71,0xbf7c3f4a3f62bf80,0xbd97becf3f2cbe79,
0x3f75bf46bf6d3f80,0xbdc93ef1bf0e3e48,0x3f62bf7fbec43f35,0x3f22be95bf7b3f55,0x3e95bf223ec40000,0x3f7fbf62bf553f7b,0xbef13dc93f6dbf35,0x3f46bf75be483f0e,
0xbe953f22bec48000,0xbf7f3f623f55bf7b,0x3ef1bdc9bf6d3f35,0xbf463f753e48bf0e,0x3f75bf46bf6d3f80,0xbdc93ef1bf0e3e48,0x3f62bf7fbec43f35,0x3f22be95bf7b3f55,
0xbe2fbdfb3f46bf0e,0x3f73bf80bf043f3e,0x3ecfbf273e950000,0x3f77bf58bf673f7d,0xbf7a3f5f3f62bf7b,0x3d97beb83f18beac,0xbf313ee63f7fbf6d,0x3f1dbf513d493e79,
0x3f7cbf7ebf223f55,0x3ea1bcc9bf5c3f2c,0x3f6abf42bf753f80,0xbe893f09bedb3e16,0x3e60befc3ef1be48,0x3f7fbf6fbf4e3f71,0x3f39bf65bdc93ec4,0x3f4abf13bf803f78,
0xbf783f803f0ebf35,0xbeac3e163f62bf46,0xbf4e3f673e48bec4,0xbf2c3f043f7fbf75,0xbf5c3f3e3f7bbf80,0x3edbbf183e95bdc9,0xbf7d3f713f55bf6d,0x3d49be793f22bef1,
0xbe793d493f55bf35,0x3f71bf7dbef13f22,0xbf183edb3f7bbf6d,0x3f3ebf5cbdc93e95,0x3f04bf2c3e488000,0x3f67bf4ebf753f7f,0x3e16beac3f0ebec4,0x3f80bf78bf463f62,
0xbd973e2fbf223f0e,0xbf803f7e3f3ebf4e,0xbe893eb8bef13ec4,0xbf7a3f733f5cbf67,0xbee63f09be953e48,0xbf6a3f5f3f71bf78,0xbf1d3f31bdc90000,0xbf513f423f7dbf80,
0xbf7f3f7c3f46bf55,0x3cc9bdfb3f2cbf18,0xbf773f6f3f62bf6d,0x3e60bea13f04bedb,0xbf653f583f75bf7b,0x3ecfbefc3eacbe79,0xbf4a3f393f7fbf80,0x3f13bf273e16bd49,
0xbf353f35bf803f80,0x3f35bf3500000000,0xbf353f35bf803f80,0x3f35bf3500000000,0xbf353f35bf803f80,0x3f35bf3500000000,0xbf353f35bf803f80,0x3f35bf3500000000,
0x3f35bf3580008000,0x3f35bf353f80bf80,0x3f35bf3580008000,0x3f35bf353f80bf80,0x3f35bf3580008000,0x3f35bf353f80bf80,0x3f35bf3580008000,0x3f35bf353f80bf80,
0xbf65bf583f623f55,0xbf6abf5f3f673f5c,0xbf4abf393f463f35,0xbf51bf423f4e3f3e,0xbf7fbf7c3f7f3f7b,0xbf80bf7e3f803f7d,0xbf77bf6f3f753f6d,0xbf7abf733f783f71,
0xbee6bf093ef13f0e,0xbecfbefc3edb3f04,0xbf1dbf313f223f35,0xbf13bf273f183f2c,0xbd97be2f3dc93e48,0xbcc9bdfb3d493e16,0xbe89beb83e953ec4,0xbe60bea13e793eac,
0xbf5cbf3e3f553f35,0xbf67bf4e3f623f46,0xbf7dbf713f7b3f6d,0xbf80bf783f7f3f75,0xbe79bd493e480000,0xbeacbe163e953dc9,0xbf18bedb3f0e3ec4,0xbf2cbf043f223ef1,
0xbf04bf2c3f0e3f35,0xbedbbf183ef13f22,0xbe16beac3e483ec4,0xbd49be793dc93e95,0xbf78bf803f7b3f80,0xbf71bf7d3f753f7f,0xbf4ebf673f553f6d,0xbf3ebf5c3f463f62,
0xbf7abf5f3f753f55,0xbf7fbf6f3f7d3f67,0xbf31bee63f223ec4,0xbf4abf133f3e3f04,0xbe2f3dfb3dc9be48,0xbea1bcc93e79bd49,0x3ecf3f27bef1bf35,0x3e893f09beacbf18,
0xbe60befc3e953f0e,0xbd97beb83e163edb,0xbf39bf653f463f6d,0xbf1dbf513f2c3f5c,0xbf7cbf7e3f7f3f7b,0xbf73bf803f783f80,0xbf6abf423f623f35,0xbf77bf583f713f4e,
0x3f623f7fbf6dbf80,0x3f463f75bf55bf7b,0x3e953f22bec4bf35,0x3dc93ef1be48bf0e,0xbef1bdc93ec40000,0xbf22be953f0e3e48,0xbf75bf463f6d3f35,0xbf7fbf623f7b3f55,
0xbef1bdc93ec48000,0xbf22be953f0e3e48,0xbf75bf463f6d3f35,0xbf7fbf623f7b3f55,0xbf62bf7f3f6d3f80,0xbf46bf753f553f7b,0xbe95bf223ec43f35,0xbdc9bef13e483f0e,
0x3f313f73bf46bf7b,0x3efc3f58bf18bf67,0x3f7c3f4abf75bf35,0x3f7f3f6abf80bf5c,0xbf6fbf273f623f0e,0xbf7ebf513f783f3e,0xbe603e893dc9bec4,0xbee63cc93eacbe16,
0xbf39bea13f223e48,0xbf5fbf093f4e3edb,0x3e2f3f1dbe95bf35,0xbd973ecfbd49bf04,0xbeb8bf423ef13f55,0xbdfbbf133e793f2c,0xbf7abf773f7f3f6d,0xbf65bf803f713f7d,
0x3d493f18be48bf35,0xbe793eac3dc9bef1,0xbf67bf043f553ec4,0xbf7dbf3e3f753f22,0x3f2c3e16bf0e0000,0x3f5c3edbbf46be95,0x3f713f78bf7bbf6d,0x3f4e3f80bf62bf7f,
0xbf80bf4e3f7b3f35,0xbf78bf713f7f3f62,0xbedbbf5c3f0e3f6d,0xbe16bf2c3e953f46,0x3f3e3f7dbf55bf80,0x3f043f67bf22bf75,0xbeac3e793e48bec4,0xbf18bd493ef1bdc9,
0xbf5fbeb83f463e48,0xbf7cbf273f713f04,0x3ea13f58bef1bf6d,0xbcc93f1dbe16bf3e,0x3f7e3f31bf75bf0e,0x3f7a3f65bf80bf4e,0x3d97bf133dc93f35,0x3ecfbe89be793edb,
0xbefcbf6f3f223f7b,0xbe2fbf423eac3f5c,0xbf73bf093f623ec4,0xbf80bf4a3f7d3f2c,0x3dfb3f39be95bf55,0xbe603ee63d49bf18,0x3f7f3f51bf7fbf35,0x3f6a3f77bf78bf67,
0xbf0ebf7b3f353f80,0xbe48bf553ec43f6d,0x3f553e48bf350000,0x3f7b3f0ebf6dbec4,0x3f0e3f7bbf35bf80,0x3e483f55bec4bf6d,0xbf55be483f350000,0xbf7bbf0e3f6d3ec4,
0x3f553e48bf358000,0x3f7b3f0ebf6dbec4,0x3f0e3f7bbf35bf80,0x3e483f55bec4bf6d,0xbf55be483f358000,0xbf7bbf0e3f6d3ec4,0xbf0ebf7b3f353f80,0xbe48bf553ec43f6d,
0x3efcbeb8be953f0e,0x3f513d97bf2c3e16,0xbf73bf583f7f3f35,0xbf39bf7e3f5c3f71,0xbf4abcc93f22be48,0xbf7abee63f673e79,0x3f423f7cbf62bf6d,0x3ecf3f77bf18bf80,
0x3f5f3f6fbf75bf55,0x3f133f7fbf3ebf7d,0x3ea1bf09bdc93f35,0x3f31bdfbbf043eac,0xbf1dbf803f463f7b,0xbe60bf653edb3f78,0xbf273e2f3ef1bec4,0xbf6abe893f4e3d49,
0x3f673f5cbf7bbf35,0x3f183f80bf46bf75,0xbf3e3e163f0ebec4,0xbf78beac3f623dc9,0xbf71be793f550000,0xbf7dbf2c3f7f3ef1,0x3d49bf4e3e483f6d,0x3f04bedbbe953f22,
0xbedb3f043e48bf35,0xbf4e3d493f22be95,0xbf2cbf7d3f553f6d,0xbe79bf713ef13f7f,0xbeacbf783f0e3f80,0x3e16bf3e3dc93f62,0x3f803f18bf7bbec4,0x3f5c3f67bf75bf46,
0xbf313ea13ef1bf0e,0xbf77be603f5cbd49,0x3f7c3f1dbf7fbec4,0x3f423f6fbf67bf4e,0xbecfbf7f3f223f7b,0x3dfbbf513e163f71,0xbf093efc3e95bf35,0xbf65bcc93f3ebe79,
0xbf39bf733f623f55,0xbe89bf7a3f043f80,0xbe2f3f4abdc9bf6d,0xbf273eb83edbbf18,0x3f6a3d97bf463e48,0x3f7e3f13bf7dbeac,0xbf58bf5f3f753f35,0xbee6bf803f2c3f78,
0x3dc93f75bec4bf80,0xbef13f223e48bf55,0xbf46bf623f6d3f35,0xbe95bf7f3f0e3f7b,0x3f7f3e95bf6d0000,0x3f623f46bf7bbf0e,0xbf223ef13ec4bf35,0xbf75bdc93f55be48,
0xbf7fbe953f6d8000,0xbf62bf463f7b3f0e,0x3f22bef1bec43f35,0x3f753dc9bf553e48,0x3dc93f75bec4bf80,0xbef13f223e48bf55,0xbf46bf623f6d3f35,0xbe95bf7f3f0e3f7b,
0xbf7abefc3f7f3e48,0xbf27bf6a3f5c3f3e,0x3f313f65bf62bf35,0x3dfb3f7cbedbbf7d,0xbf133f1d3e95bf55,0xbf733cc93f4ebeac,0x3f6fbd97bf463ec4,0x3f773f09bf80be79,
0x3e60bf5f3dc93f7b,0x3f42becfbf043f2c,0xbf393ee63ef1bf35,0xbf7ebe2f3f67be16,0xbf51bf4a3f753f0e,0xbea1bf803f183f71,0x3eb83f7fbf22bf6d,0xbe893f58bd49bf78,
0x3f4ebedbbf0e3f35,0x3f803e79bf753dc9,0xbf043f3e3e48bf6d,0xbf713e163f46bef1,0x3f7d3eacbf7b0000,0x3f2c3f5cbf62bf22,0xbf783d493f55bec4,0xbf67bf183f7f3e95,
0x3f183f67bf55bf35,0xbd493f78be95bf7f,0xbf5cbf2c3f7b3ec4,0xbeacbf7d3f223f62,0xbe163f71be48bf80,0xbf3e3f043ef1bf46,0xbe79bf803f0e3f6d,0x3edbbf4ebdc93f75,
0xbee63f583dc9bf7b,0xbf6f3e893f3ebf18,0x3f1dbf39be953f6d,0x3f7cbd97bf5c3edb,0xbf423f133ef1bf55,0xbf80bdfb3f71be79,0x3f5fbecfbf223f35,0x3f7a3ea1bf7d3d49,
0xbf65bf093f7f3e48,0xbeb8bf773f2c3f4e,0x3f4a3f31bf75bec4,0x3e2f3f7fbf04bf67,0xbf27bf513f623f0e,0x3cc9bf7e3eac3f78,0x3efc3f6abf46bf35,0xbe603f73be16bf80,
0x3ec4bf6d00003f80,0x3f6dbec4bf353f35,0xbec43f6d0000bf80,0xbf6d3ec43f35bf35,0x3ec4bf6d00003f80,0x3f6dbec4bf353f35,0xbec43f6d0000bf80,0xbf6d3ec43f35bf35,
0x3f6d3ec4bf808000,0x3ec43f6dbf35bf35,0xbf6dbec43f808000,0xbec4bf6d3f353f35,0x3f6d3ec4bf808000,0x3ec43f6dbf35bf35,0xbf6dbec43f808000,0xbec4bf6d3f353f35,
0x3d973f7cbef1bf55,0xbf313f4a3eacbf78,0xbe89bf6f3f223f35,0x3f09bf65be163f80,0xbea13f7abdc9bf7b,0xbf6a3efc3f2cbf4e,0x3dfbbf803e953f6d,0x3f51bf27bf043f67,
0xbf7f3e2f3f62bf0e,0xbf39bf1d3f713e79,0x3f77beb8bf463f35,0x3f583ee6bf7dbd49,0xbf73be603f7fbe48,0xbecfbf5f3f3e3f18,0x3f7e3cc9bf753ec4,0x3f133f42bf5cbedb,
0xbe16bf713f0e3f35,0x3f2cbf5cbe953f7f,0xbe793f80be48bf6d,0xbf673f183f22bf62,0xbf4ebedb3f7b0000,0xbd49bf783ef13f46,0x3f043f3ebf55bec4,0xbeac3f7dbdc9bf75,
0x3f7dbeacbf553f35,0x3f3e3f04bf75bdc9,0xbf78bd493f7bbec4,0xbedbbf4e3f463ef1,0x3f18bf67be483f80,0x3f80be79bf623f22,0xbf5c3f2c3f0ebf6d,0xbf71be163f7fbe95,
0xbe2f3f7ebe95bf55,0xbf653f313f18bf71,0xbecfbf423f463ec4,0x3efcbf7abd493f78,0x3f583e89bf7f3e48,0x3d973f6fbf04bf2c,0xbf803ea13f62bf35,0xbf1dbf133f673e16,
0xbf7c3dfb3f75bf0e,0xbee6bf393f4e3eac,0x3f6abf27bf223f6d,0x3f5f3e60bf803e79,0xbf093f773dc9bf7b,0xbf7f3eb83f5cbf3e,0xbcc9bf733ef13f35,0x3f4abf51bedb3f7d,
0xbf463f623ec4bf80,0xbf753dc93f7bbf0e,0x3f7fbe95bf6d3f35,0x3ef13f22bf55be48,0xbf22bef13f6d0000,0x3e95bf7f3e483f55,0xbdc93f75bec4bf35,0xbf623f463f0ebf7b,
0xbf22bef13f6d8000,0x3e95bf7f3e483f55,0xbdc93f75bec4bf35,0xbf623f463f0ebf7b,0x3f46bf62bec43f80,0x3f75bdc9bf7b3f0e,0xbf7f3e953f6dbf35,0xbef1bf223f553e48,
0x3f6fbf42bf223f7b,0x3f4a3e2fbf7d3eac,0xbe603f77be95bf35,0xbf733f393f2cbf78,0xbcc93f65bef1bf0e,0xbf5f3f583f04bf80,0xbf51bdfb3f7fbec4,0x3d97bf6a3edb3f18,
0x3eb83f27bf46be48,0xbf1d3f7c3e16bf71,0xbf7a3e893f75bf35,0xbea1bf313f3e3e79,0xbf803ee63f62bf55,0xbefcbf093f5c3d49,0x3f13bf7ebdc93f6d,0x3f7fbecfbf673f4e,
0xbf713e793f7bbf35,0xbe16bf3e3f223e95,0x3d493f4ebf0ebec4,0xbf5c3f673ef1bf7f,0x3edb3f04bf550000,0xbf183f803dc9bf62,0x3f2cbf7dbe483f6d,0x3f78beacbf753f46,
0x3eacbf783e483f35,0x3f7dbf2cbf463f75,0xbf803f183f55bf6d,0xbf04bedb3f62bdc9,0xbf673f5c3f0ebf80,0xbf4ebd493f7fbef1,0x3f3e3e16bf7b3ec4,0xbe793f71be95bf22,
0x3dfb3f31bf22be48,0xbf583f733edbbf78,0xbf7f3f133f62bf6d,0xbeb8befc3f4ebd49,0x3e89bf6a3e953f0e,0x3f7cbf42bf3e3f7d,0x3f65be60bf7f3f35,0xbcc93f4abf04beac,
0xbf7e3f393f46bf7b,0xbf09bea13f67be79,0x3d97bf513ef13ec4,0x3f6fbf5fbf183f80,0x3f77becfbf753f55,0x3e2f3f27bf2cbe16,0xbee63f7abdc9bf35,0xbf803f1d3f5cbf71,
0x3f7bbf55bf353f80,0x3f0e3e48bf6d3ec4,0xbe48bf0e3f350000,0x3f55bf7bbec43f6d,0xbf7b3f553f35bf80,0xbf0ebe483f6dbec4,0x3e483f0ebf350000,0xbf553f7b3ec4bf6d,
0x3e483f0ebf358000,0xbf553f7b3ec4bf6d,0x3f7bbf55bf353f80,0x3f0e3e48bf6d3ec4,0xbe48bf0e3f358000,0x3f55bf7bbec43f6d,0xbf7b3f553f35bf80,0xbf0ebe483f6dbec4,
0xbf1dbcc93f75bf0e,0x3f09bf733d493f18,0x3f27bf7cbdc93f35,0x3f6fbefcbf783f67,0x3e893ecfbf463e48,0xbf513f7f3eacbf5c,0xbf653f7a3ef1bf6d,0xbf393dfb3f7dbf2c,
0x3f4abf80be953f55,0x3f58bea1bf803f4e,0x3f42be2fbf7f3f35,0xbeb83f5fbe79bedb,0xbf773f6a3f22bf7b,0xbf13bd973f71bf04,0xbee6be603f62bec4,0x3f31bf7ebe163f3e,
0xbf3e3f7d3e48bf35,0xbf5c3edb3f7fbf62,0x3eac3e79bf553ec4,0xbf4e3f803e95bf46,0x3d49bf183f0e0000,0x3f78bf71bf223f75,0xbf673f043f7bbf6d,0x3e16bf2c3ef13dc9,
0xbf2c3e163f7bbf35,0x3f04bf673dc93ef1,0xbf713f783f0ebf6d,0xbf183d493f75bf22,0x3f80bf4ebf553f80,0x3e793eacbf463e95,0x3edbbf5c3e483ec4,0x3f7dbf3ebf623f7f,
0x3ecf3d97bf623f0e,0xbf4a3f7c3e79bf2c,0xbf093f5fbdc9bec4,0xbf733f313f71bf7d,0xbf803f653f46bf7b,0xbe89be603f4ebedb,0xbf133dfb3f75bf35,0x3f27bf6fbd493f04,
0xbf6a3f7f3ef1bf55,0xbf1d3e2f3f78bf3e,0xbf583efc3f7fbf6d,0x3ea1bf393eac3e16,0xbcc9bee63f22be48,0x3f77bf7abf183f67,0x3f51bf7ebe953f35,0x3f42beb8bf803f5c,
0xbf753f463f6dbf80,0x3dc9bef13f0ebe48,0xbf623f7f3ec4bf35,0xbf223e953f7bbf55,0xbe953f22bec40000,0xbf7f3f623f55bf7b,0x3ef1bdc9bf6d3f35,0xbf463f753e48bf0e,
0x3e95bf223ec48000,0x3f7fbf62bf553f7b,0xbef13dc93f6dbf35,0x3f46bf75be483f0e,0xbf753f463f6dbf80,0x3dc9bef13f0ebe48,0xbf623f7f3ec4bf35,0xbf223e953f7bbf55,
0xbf133f4abdc9be48,0xbf653f393f78bf80,0xbf6f3f7f3ef1bf35,0xbefc3e603f71bf4e,0x3f09be89bf753f55,0xbf423f6a3e16bedb,0xbcc93ea1bf223ec4,0xbf7e3f7c3f2cbf5c,
0xbf513f1d3f7fbf7b,0x3ee6bf313e793d49,0xbeb83d973f62bf35,0x3f5fbf7abeac3f18,0xbf583f773e95bf0e,0xbf273ecf3f7dbf67,0xbf803f733f46bf6d,0xbdfbbe2f3f3ebf04,
0x3e79bd49bf553f35,0xbf713f7d3ef1bf22,0x3f18bedbbf7b3f6d,0xbf3e3f5c3dc9be95,0xbf043f2cbe480000,0xbf673f4e3f75bf7f,0xbe163eacbf0e3ec4,0xbf803f783f46bf62,
0xbf783f803f0ebf35,0xbeac3e163f62bf46,0xbf4e3f673e48bec4,0xbf2c3f043f7fbf75,0xbf5c3f3e3f7bbf80,0x3edbbf183e95bdc9,0xbf7d3f713f55bf6d,0x3d49be793f22bef1,
0x3f27bf13bf7f3f7b,0xbf393f4a3d49be16,0x3efcbecfbf753f6d,0xbf583f653e79beac,0x3ea1be60bf623f55,0xbf6f3f773edbbf04,0x3dfbbcc9bf463f35,0xbf7c3f7f3f18bf2c,
0xbf423f513dc9be48,0xbf313f1d3f80bf7d,0xbf5f3f6a3e95bec4,0xbf093ee63f78bf71,0xbf733f7a3ef1bf0e,0xbeb83e893f67bf5c,0xbf7e3f803f22bf35,0xbe2f3d973f4ebf3e,
0x3f35bf35bf803f80,0xbf353f3500000000,0x3f35bf35bf803f80,0xbf353f3500000000,0x3f35bf35bf803f80,0xbf353f3500000000,0x3f35bf35bf803f80,0xbf353f3500000000,
0x3f35bf3580008000,0x3f35bf35bf803f80,0x3f35bf3580008000,0x3f35bf35bf803f80,0x3f35bf3580008000,0x3f35bf35bf803f80,0x3f35bf3580008000,0x3f35bf35bf803f80,
0x3ea13e603f753f7b,0xbeb8be89bf71bf78,0x3dfb3cc93f7f3f80,0xbe2fbd97bf7dbf80,0x3f273f133f463f55,0xbf31bf1dbf3ebf4e,0x3efc3ecf3f623f6d,0xbf09bee6bf5cbf67,
0x3f733f7abe95be48,0xbf6fbf773eac3e79,0x3f7e3f80bdc98000,0xbf7cbf7f3e163d49,0x3f423f51bf22bf0e,0xbf39bf4a3f2c3f18,0x3f5f3f6abef1bec4,0xbf58bf653f043edb,
0x3f5c3f3e3f0e3f35,0xbf67bf4ebef1bf22,0x3f7d3f713e483ec4,0xbf80bf78bdc9be95,0x3e793d493f7b3f80,0xbeacbe16bf75bf7f,0x3f183edb3f553f6d,0xbf2cbf04bf46bf62,
0x3f043f2cbf55bf35,0xbedbbf183f623f46,0x3e163eacbf7bbf6d,0xbd49be793f7f3f75,0x3f783f80be488000,0xbf71bf7d3e953dc9,0x3f4e3f67bf0ebec4,0xbf3ebf5c3f223ef1,
0x3f583f77bef1be48,0xbf42bf6a3f183eac,0x3f803f733dc93ec4,0xbf7ebf7c3d49be79,0x3f513f1d3f223f55,0xbf65bf39bf04bf3e,0x3eb83d973f753f80,0xbefcbe60bf67bf7d,
0xbf09be89bf62bf7b,0x3f273ecf3f4e3f71,0x3cc93ea1bf7fbf6d,0x3dfbbe2f3f803f78,0x3f133f4abf46bf0e,0xbee6bf313f5c3f2c,0x3f6f3f7fbe958000,0xbf5fbf7a3edb3e16,
0x3ef13dc93f6d3f80,0xbf22be95bf55bf7b,0x3f753f463ec43f35,0xbf7fbf62be48bf0e,0x3f623f7fbec40000,0xbf46bf753f0e3e48,0x3e953f22bf6dbf35,0xbdc9bef13f7b3f55,
0x3f623f7fbec48000,0xbf46bf753f0e3e48,0x3e953f22bf6dbf35,0xbdc9bef13f7b3f55,0xbef1bdc9bf6dbf80,0x3f223e953f553f7b,0xbf75bf46bec4bf35,0x3f7f3f623e483f0e,
0x3f803f653dc93f0e,0xbf77bf7a3e16beac,0x3f133dfb3f623f80,0xbf42beb8bf3ebf78,0xbecf3d97bf75bf7b,0x3f1d3e2f3f5c3f80,0x3f093f5fbf46bec4,0xbea1bf393f673f18,
0xbcc93ee6bf7fbf55,0x3e89be603f7d3f71,0x3f513f7ebef18000,0xbf27bf6f3f2c3e79,0xbf6abf7f3e95be48,0x3f4a3f7cbf04bd49,0xbf58befcbf22bf6d,0x3f733f313edb3f4e,
0x3d493f18bf7bbf35,0x3e79beac3f7f3f62,0xbf67bf04bf0ebf6d,0x3f7d3f3e3e953f46,0x3f2c3e163f553f80,0xbf5cbedbbf22bf75,0x3f713f78be483ec4,0xbf4ebf803ef1bdc9,
0xbf80bf4ebe48bf35,0x3f783f71bdc93ef1,0xbedbbf5c3f553ec4,0x3e163f2cbf75bf22,0x3f3e3f7dbf0e8000,0xbf04bf673f463e95,0xbeac3e79bf7bbf6d,0x3f183d493f623f7f,
0xbf77bf6a3dc9bf0e,0x3f513f7fbedb3e79,0xbee63e60bf75bf6d,0x3f393dfb3f4e3f80,0x3f4a3f80bef13e48,0xbf09bf733f3e3e16,0x3f423e2f3f463f80,0xbf6fbefcbf04bf71,
0x3e89becf3f7f3f55,0xbf133d97bf67bf78,0xbf65bf7a3e95bec4,0x3f313f7ebf183d49,0xbf1d3cc9bf62bf7b,0x3f583ea13f2c3f7d,0x3f273f7cbf228000,0xbeb8bf5f3f5c3eac,
0x3f553e483f353f80,0xbf7bbf0ebec4bf6d,0x3f0e3f7bbf350000,0xbe48bf553f6d3ec4,0xbf55be48bf35bf80,0x3f7b3f0e3ec43f6d,0xbf0ebf7b3f350000,0x3e483f55bf6dbec4,
0x3f0e3f7bbf358000,0xbe48bf553f6d3ec4,0xbf55be48bf35bf80,0x3f7b3f0e3ec43f6d,0xbf0ebf7b3f358000,0x3e483f55bf6dbec4,0x3f553e483f353f80,0xbf7bbf0ebec4bf6d,
0x3e893f6abf62be48,0x3e2fbf273f803f18,0x3f653e603f223f80,0xbf80bf1dbe79bf67,0x3dfbbf313f7f3f0e,0xbf093ea1bf71bf5c,0xbf7fbf13be95bf6d,0x3f6f3f5fbe163f2c,
0xbf77becfbef1bf7b,0x3f7c3f423d493f4e,0x3ee63f7abf468000,0xbcc9bf4a3f783edb,0x3f7e3f393dc93f55,0xbf58bf733eacbf04,0xbd97bf513f753ec4,0xbeb83efcbf7dbf3e,
0xbf67bf5c3e48bf35,0x3f183f80bf223e95,0x3f3ebe163f553f6d,0xbf78beacbef1bf7f,0x3f713e793f0e3f80,0xbf7dbf2cbdc9bf62,0xbd493f4ebf7bbec4,0x3f04bedb3f753f46,
0x3edbbf043f7b3f35,0xbf4e3d49bf46bf75,0x3f2c3f7dbf0e3ec4,0xbe79bf713f623dc9,0x3eac3f78bf558000,0x3e16bf3e3f7f3ef1,0xbf80bf18be48bf6d,0x3f5c3f67be953f22,
0x3f803ee63e953f7b,0xbf5fbf583e79bf3e,0xbf13bf7e3f22bec4,0x3d973f6abf71be16,0xbeb83f27bf7fbf0e,0x3f4abe2f3f4e3f67,0x3f7a3e893ef13f80,0xbf73bf393d49bf5c,
0x3cc93f65bf75be48,0x3efcbf093f783f2c,0x3f51bdfb3f463f6d,0xbf7fbecfbeacbf7d,0xbf6fbf423dc9bf55,0x3f1d3f7cbf183edb,0x3e603f77bf628000,0x3ea1bf313f803f04,
0x3f7f3e953ec43f80,0xbf62bf463e48bf55,0xbf223ef1bf6dbf35,0x3f753dc93f0e3f7b,0xbdc9bf753f6d0000,0xbef13f22bf7bbf0e,0x3f463f62bec43f35,0xbe95bf7f3f55be48,
0x3dc93f75bf6d8000,0x3ef1bf223f7b3f0e,0xbf46bf623ec4bf35,0x3e953f7fbf553e48,0x3f7f3e953ec43f80,0xbf62bf463e48bf55,0xbf223ef1bf6dbf35,0x3f753dc93f0e3f7b,
0xbf583e89bf46bf55,0x3f7f3eb83e793f80,0x3f803ea13e953f80,0xbf4abf513eacbf4e,0x3e2f3f7ebf623e48,0x3ee6bf393f7d3edb,0x3ecfbf423f7f3ec4,0xbf5f3e60bf3ebf5c,
0xbf09bf773f22bf0e,0xbd973f6fbf78bd49,0xbcc93f73bf758000,0x3f1dbf133f713f18,0xbf7cbdfbbef1bf7b,0x3f653f31be163f67,0x3f6a3f27bdc93f6d,0xbefcbf7a3f2cbf04,
0x3f4ebedb3f553f35,0xbf80be79be95bf7f,0xbf043f3ebf7bbec4,0x3f71be163f223f62,0x3f7d3eac3e483f80,0xbf2cbf5c3ef1bf46,0xbf783d49bf0ebf6d,0x3f673f18bdc93f75,
0x3f183f67bf0e3f35,0x3d49bf783f75bdc9,0xbf5cbf2c3e48bf6d,0x3eac3f7dbf463ef1,0xbe163f71bf7b8000,0x3f3ebf043f623f22,0xbe79bf803f55bec4,0xbedb3f4ebf7fbe95,
0xbf733e60bf22bf55,0x3f6a3efcbd493f7d,0x3f7ebcc93ef13f6d,0xbf51bf273e79bf71,0xbf7fbe2fbe95bf7b,0x3f313f4abedb3f5c,0x3f773eb83dc93f80,0xbf09bf653f18bf3e,
0xbea1bf7a3f46bf0e,0xbecf3f5fbf80be16,0x3dfb3f80bf623ec4,0x3f13bf423f783eac,0x3d97bf7c3f75be48,0xbf393f1dbf67bf04,0xbe893f6fbf7f8000,0x3f58bee63f4e3f2c,
0x3f6d3ec400003f80,0xbec4bf6d3f35bf35,0xbf6dbec40000bf80,0x3ec43f6dbf353f35,0x3f6d3ec400003f80,0xbec4bf6d3f35bf35,0xbf6dbec40000bf80,0x3ec43f6dbf353f35,
0xbec43f6dbf808000,0x3f6dbec43f353f35,0x3ec4bf6d3f808000,0xbf6d3ec4bf35bf35,0xbec43f6dbf808000,0x3f6dbec43f353f35,0x3ec4bf6d3f808000,0xbf6d3ec4bf35bf35,
0xbf42bf133e95bf7b,0x3cc93f7ebf673f04,0x3f5f3ecfbdc93f80,0xbe60bf733f4ebf2c,0xbee6bf583f22bf55,0xbeb83f77bf803e16,0x3f1d3f39bef13f6d,0x3e2fbf7f3f78beac,
0x3f27bf513f753e48,0xbf803dfbbedbbf5c,0xbefc3f6abf7f8000,0x3f7abea13f183f3e,0x3f65bf093f463f0e,0xbf6fbe89bd49bf7d,0xbf4a3f31bf62bec4,0x3f7c3d973e793f71,
0x3e163f71bf553f35,0x3f2cbf5c3f753dc9,0x3e79bf803f7bbec4,0xbf673f18bf46bef1,0x3f4e3edbbe483f80,0xbd49bf783f62bf22,0xbf04bf3e3f0ebf6d,0xbeac3f7dbf7f3e95,
0xbf7d3eacbf0ebf35,0x3f3e3f04be953f7f,0x3f783d493e483f6d,0xbedbbf4e3f22bf62,0xbf183f67bf7b8000,0x3f80be793ef13f46,0x3f5cbf2c3f553ec4,0xbf71be16bdc9bf75,
0x3f51bf4a3f623e48,0xbf73bcc9be16bf67,0xbeb83f7fbf7f3ec4,0x3f77bf093f2c3f04,0xbe60bf5f3f46bf55,0xbf273f6abf783d49,0x3f393ee6be953f80,0x3dfbbf7c3f71bf18,
0x3f133f1dbef13f7b,0x3ea1bf803f7dbedb,0xbf6fbd97bdc9bf6d,0x3e893f58bf3e3f5c,0x3f7abefc3f223f0e,0xbf42becf3e79bf80,0xbf313f65bf758000,0x3f7ebe2f3eac3f4e,
0x3f223ef1bec43f80,0x3e95bf7f3f7bbf0e,0x3dc9bf753f6dbf35,0xbf623f46bf55be48,0xbf463f62bf6d0000,0x3f75bdc93e483f55,0x3f7fbe953ec43f35,0xbef1bf223f0ebf7b,
0xbf463f62bf6d8000,0x3f75bdc93e483f55,0x3f7fbe953ec43f35,0xbef1bf223f0ebf7b,0xbf22bef13ec4bf80,0xbe953f7fbf7b3f0e,0xbdc93f75bf6d3f35,0x3f62bf463f553e48,
0x3ecfbf7f3f7fbf0e,0xbf7e3f13bf18bedb,0x3f093efcbef13f80,0x3ee6bf803f80bf04,0x3f313ea1be953f7b,0x3e89bf7a3f78bf2c,0xbf7c3f1dbf22bec4,0x3f273eb8beac3f7d,
0x3f6abd973dc93f55,0xbdfbbf513f4ebf67,0xbf583f5fbf628000,0x3f65bcc93d493f5c,0xbf393f73bf753e48,0x3f77be603e793f3e,0xbe2fbf4a3f46bf6d,0xbf423f6fbf713e16,
0xbf713e79be48bf35,0x3e163f3ebf463f75,0x3d493f4ebf553f6d,0x3f5cbf673f62bdc9,0x3edb3f04bf0e3f80,0x3f18bf803f7fbef1,0x3f2cbf7d3f7bbec4,0xbf783eacbe95bf22,
0x3eacbf783f7bbf35,0xbf7d3f2cbf22be95,0xbf803f18bf0ebec4,0x3f043edbbef13f7f,0xbf673f5cbf558000,0x3f4e3d49bdc93f62,0x3f3e3e16be483f6d,0x3e79bf713f75bf46,
0xbf1d3f80bf7f3f0e,0x3f7abee63eac3f04,0xbf27be2f3e95bf6d,0xbecf3f77bf7d3f3e,0x3f5fbf6f3f62be48,0xbf513d973d49bf4e,0x3ea13f09bf223f80,0x3f39bf7e3f78bedb,
0xbf4a3cc93dc9bf55,0xbe603f65bf713f5c,0x3f42bf7c3f75bec4,0xbf6a3e89be16bf2c,0x3efc3eb8bef13f7b,0x3f13bf7f3f80bf18,0xbf733f58bf468000,0x3f313dfbbe793f67,
0x3e483f0ebf353f80,0x3f55bf7b3f6dbec4,0x3f7bbf553f350000,0xbf0ebe483ec4bf6d,0xbe48bf0e3f35bf80,0xbf553f7bbf6d3ec4,0xbf7b3f55bf350000,0x3f0e3e48bec43f6d,
0xbf7b3f55bf358000,0x3f0e3e48bec43f6d,0x3e483f0ebf353f80,0x3f55bf7b3f6dbec4,0x3f7bbf553f358000,0xbf0ebe483ec4bf6d,0xbe48bf0e3f35bf80,0xbf553f7bbf6d3ec4,
0x3f7ebf313ef13e48,0xbe60bee63f2cbf7d,0x3d973f13bf463f80,0x3f6abf773f5cbeac,0xbf5f3eb8bdc9bf0e,0xbe2f3f42bf673f78,0x3ea1bf583f75bf6d,0xbf803f4abf18bd49,
0xbdfb3f39bf623f7b,0x3f7abf653f3ebe16,0xbf7f3f51bf228000,0x3ecf3e89bf043f71,0x3efcbf6f3f7fbf55,0xbf7c3f27bedbbe79,0x3f73bf093e953ec4,0xbcc9bf1d3f4ebf80,
0x3f3ebf7d3f7bbf35,0xbf5c3edbbdc9bef1,0xbeacbe793f0ebf6d,0xbf4e3f80bf753f22,0xbd493f18bf553f80,0x3f78bf713f46be95,0x3f67bf043e483ec4,0x3e16bf2c3f62bf7f,
0x3f2cbe16be483f35,0x3f04bf673f7fbf62,0x3f71bf783f55bec4,0xbf183d493e95bf46,0xbf803f4ebf0e8000,0x3e793eacbf223f75,0xbedb3f5cbf7b3f6d,0x3f7dbf3e3ef13dc9,
0x3eb8bf423f75bf7b,0xbf7e3f51bf043d49,0x3f7abf773f46bec4,0xbee6bcc93edbbf4e,0x3f39bea1bdc93f0e,0x3efcbf583f7dbf71,0xbe2f3f1dbf623f80,0x3f7fbf6a3f2cbe79,
0x3f6fbf273e953e48,0x3dfbbf133f5cbf80,0x3e603e89bf223f6d,0x3f65bf803f67bf18,0xbf313f73bf7f3f55,0x3f5fbf093e163eac,0xbf7c3f4abef18000,0x3d973ecfbf3e3f78,
0xbe953f22bf6d3f80,0x3f7fbf623f0ebe48,0x3ef1bdc9bec43f35,0x3f46bf753f7bbf55,0x3f75bf463ec40000,0x3dc9bef13f55bf7b,0x3f62bf7f3f6dbf35,0xbf223e953e48bf0e,
0xbf753f46bec48000,0xbdc93ef1bf553f7b,0xbf623f7fbf6d3f35,0x3f22be95be483f0e,0xbe953f22bf6d3f80,0x3f7fbf623f0ebe48,0x3ef1bdc9bec43f35,0x3f46bf753f7bbf55,
0x3e2f3dfbbf223f55,0x3f73bf803f5cbf2c,0xbecf3f27bf753f80,0x3f77bf583edbbe16,0x3f7abf5f3ef1be48,0x3d97beb83f4ebf71,0x3f31bee6bdc93ec4,0x3f1dbf513f80bf78,
0xbf7c3f7ebf463f0e,0x3ea1bcc9bf043f3e,0xbf6a3f42be958000,0xbe893f09bf673f7d,0xbe603efcbf623f7b,0x3f7fbf6f3f18beac,0xbf393f65bf7f3f6d,0x3f4abf133d493e79,
0x3e79bd49bf0e3f35,0x3f71bf7d3f62bf46,0x3f18bedbbe483ec4,0x3f3ebf5c3f7fbf75,0xbf043f2cbf7b3f80,0x3f67bf4e3e95bdc9,0xbe163eacbf553f6d,0x3f80bf783f22bef1,
0xbf783f80bf553f35,0x3eacbe16bef13f22,0xbf4e3f67bf7b3f6d,0x3f2cbf04bdc93e95,0xbf5c3f3ebe488000,0xbedb3f18bf753f7f,0xbf7d3f71bf0e3ec4,0xbd493e79bf463f62,
0xbd973e2fbf463f55,0x3f80bf7e3f2cbf18,0xbe893eb8bf623f6d,0x3f7abf733f04bedb,0xbee63f09bf753f7b,0x3f6abf5f3eacbe79,0xbf1d3f31bf7f3f80,0x3f51bf423e16bd49,
0xbf7f3f7cbf223f0e,0xbcc93dfbbf3e3f4e,0xbf773f6fbef13ec4,0xbe603ea1bf5c3f67,0xbf653f58be953e48,0xbecf3efcbf713f78,0xbf4a3f39bdc98000,0xbf133f27bf7d3f80,
0x3f35bf35bf803f80,0xbf353f3500000000,0x3f35bf35bf803f80,0xbf353f3500000000,0x3f35bf35bf803f80,0xbf353f3500000000,0x3f35bf35bf803f80,0xbf353f3500000000,
0x3f35bf3580008000,0x3f35bf35bf803f80,0x3f35bf3580008000,0x3f35bf35bf803f80,0x3f35bf3580008000,0x3f35bf35bf803f80,0x3f35bf3580008000,0x3f35bf35bf803f80,
0x3f653f583ef13f0e,0xbf6abf5fbedbbf04,0x3f4a3f393f223f35,0xbf51bf42bf18bf2c,0x3f7f3f7c3dc93e48,0xbf80bf7ebd49be16,0x3f773f6f3e953ec4,0xbf7abf73be79beac,
0x3ee63f09bf62bf55,0xbecfbefc3f673f5c,0x3f1d3f31bf46bf35,0xbf13bf273f4e3f3e,0x3d973e2fbf7fbf7b,0xbcc9bdfb3f803f7d,0x3e893eb8bf75bf6d,0xbe60bea13f783f71,
0x3f043f2cbf55bf35,0xbedbbf183f623f46,0x3e163eacbf7bbf6d,0xbd49be793f7f3f75,0x3f783f80be480000,0xbf71bf7d3e953dc9,0x3f4e3f67bf0ebec4,0xbf3ebf5c3f223ef1,
0xbf5cbf3ebf0ebf35,0x3f673f4e3ef13f22,0xbf7dbf71be48bec4,0x3f803f783dc93e95,0xbe79bd49bf7bbf80,0x3eac3e163f753f7f,0xbf18bedbbf55bf6d,0x3f2c3f043f463f62,
0xbf7abf5fbe95bf0e,0x3f7f3f6f3e163edb,0xbf31bee6bf46bf6d,0x3f4a3f133f2c3f5c,0xbe2f3dfbbf7fbf7b,0x3ea13cc93f783f80,0x3ecf3f27bf62bf35,0xbe89bf093f713f4e,
0xbe60befc3f753f55,0x3d973eb8bf7dbf67,0xbf39bf653f223ec4,0x3f1d3f51bf3ebf04,0xbf7cbf7e3dc9be48,0x3f733f80be793d49,0xbf6abf42bef1bf35,0x3f773f583eac3f18,
0xbef1bdc9bf6dbf80,0x3f223e953f553f7b,0xbf75bf46bec4bf35,0x3f7f3f623e483f0e,0xbf62bf7f3ec40000,0x3f463f75bf0ebe48,0xbe95bf223f6d3f35,0x3dc93ef1bf7bbf55,
0xbf62bf7f3ec48000,0x3f463f75bf0ebe48,0xbe95bf223f6d3f35,0x3dc93ef1bf7bbf55,0x3ef13dc93f6d3f80,0xbf22be95bf55bf7b,0x3f753f463ec43f35,0xbf7fbf62be48bf0e,
0xbf31bf733f223e48,0x3efc3f58bf4ebedb,0xbf7cbf4abe95bf35,0x3f7f3f6a3d493f04,0x3f6f3f273ef13f55,0xbf7ebf51be79bf2c,0x3e60be893f7f3f6d,0xbee63cc9bf71bf7d,
0x3f393ea13f463f7b,0xbf5fbf09bf18bf67,0xbe2fbf1d3f753f35,0xbd973ecfbf80bf5c,0x3eb83f42bf62bf0e,0xbdfbbf133f783f3e,0x3f7a3f77bdc93ec4,0xbf65bf803eacbe16,
0x3f803f4e3e483f35,0xbf78bf713dc9bef1,0x3edb3f5cbf55bec4,0xbe16bf2c3f753f22,0xbf3ebf7d3f0e0000,0x3f043f67bf46be95,0x3eacbe793f7b3f6d,0xbf18bd49bf62bf7f,
0x3d493f18bf7bbf35,0x3e79beac3f7f3f62,0xbf67bf04bf0ebf6d,0x3f7d3f3e3e953f46,0x3f2c3e163f553f80,0xbf5cbedbbf22bf75,0x3f713f78be483ec4,0xbf4ebf803ef1bdc9,
0xbf5fbeb8bf22bf7b,0x3f7c3f273eac3f5c,0x3ea13f58bf62bec4,0x3cc9bf1d3f7d3f2c,0x3f7e3f313e953f55,0xbf7abf653d49bf18,0x3d97bf133f7f3f35,0xbecf3e89bf78bf67,
0xbefcbf6f3f463e48,0x3e2f3f42bf71bf04,0xbf73bf09bef1bf6d,0x3f803f4a3e163f3e,0x3dfb3f39bf75bf0e,0x3e60bee63f803f4e,0x3f7f3f513dc93f35,0xbf6abf773e79bedb,
0x3f553e483f353f80,0xbf7bbf0ebec4bf6d,0x3f0e3f7bbf350000,0xbe48bf553f6d3ec4,0xbf55be48bf35bf80,0x3f7b3f0e3ec43f6d,0xbf0ebf7b3f350000,0x3e483f55bf6dbec4,
0x3f0e3f7bbf358000,0xbe48bf553f6d3ec4,0xbf55be48bf35bf80,0x3f7b3f0e3ec43f6d,0xbf0ebf7b3f358000,0x3e483f55bf6dbec4,0x3f553e483f353f80,0xbf7bbf0ebec4bf6d,
0xbefc3eb8bf75bf55,0x3f513d973f3e3f7d,0x3f733f58bdc93f35,0xbf39bf7e3f04beac,0x3f4a3cc93f463f7b,0xbf7abee6bedbbf78,0xbf42bf7c3ef1bec4,0x3ecf3f77bf4ebd49,
0xbf5fbf6f3e95bf0e,0x3f133f7fbf2c3e16,0xbea13f09bf7fbf35,0x3f31bdfb3f5c3f71,0x3f1d3f80bf223e48,0xbe60bf653f673e79,0x3f27be2f3f623f6d,0xbf6abe89bf18bf80,
0x3edbbf043f7b3f35,0xbf4e3d49bf46bf75,0x3f2c3f7dbf0e3ec4,0xbe79bf713f623dc9,0x3eac3f78bf550000,0x3e16bf3e3f7f3ef1,0xbf80bf18be48bf6d,0x3f5c3f67be953f22,
0x3f673f5cbe483f35,0xbf18bf803f22be95,0xbf3e3e16bf55bf6d,0x3f783eac3ef13f7f,0xbf71be79bf0ebf80,0x3f7d3f2c3dc93f62,0x3d49bf4e3f7b3ec4,0xbf043edbbf75bf46,
0xbf313ea1bf62bf55,0x3f773e603f043f80,0x3f7c3f1d3dc93f6d,0xbf42bf6f3edbbf18,0xbecfbf7f3f46be48,0xbdfb3f51bf7dbeac,0xbf093efcbf75bf35,0x3f653cc93f2c3f78,
0xbf39bf733ef1bf0e,0x3e893f7abf5c3d49,0xbe2f3f4abf7fbec4,0x3f27beb83f673f4e,0x3f6a3d973f223f7b,0xbf7ebf13be16bf71,0xbf58bf5f3e95bf35,0x3ee63f80bf3e3e79,
0xbf7fbe95bec4bf80,0x3f623f46be483f55,0x3f22bef13f6d3f35,0xbf75bdc9bf0ebf7b,0x3dc93f75bf6d0000,0x3ef1bf223f7b3f0e,0xbf46bf623ec4bf35,0x3e953f7fbf553e48,
0xbdc9bf753f6d8000,0xbef13f22bf7bbf0e,0x3f463f62bec43f35,0xbe95bf7f3f55be48,0xbf7fbe95bec4bf80,0x3f623f46be483f55,0x3f22bef13f6d3f35,0xbf75bdc9bf0ebf7b,
0x3f7a3efc3dc93f7b,0xbf27bf6a3f04bf2c,0xbf31bf653ef1bf35,0x3dfb3f7cbf673e16,0x3f13bf1d3f753f0e,0xbf733cc9bf18bf71,0xbf6f3d97bf22bf6d,0x3f773f093d493f78,
0xbe603f5fbf7fbe48,0x3f42becf3f5c3f3e,0x3f39bee63f623f35,0xbf7ebe2fbedbbf7d,0x3f513f4abe953f55,0xbea1bf803f4ebeac,0xbeb8bf7f3f46bec4,0xbe893f58bf80be79,
0xbf18bf673f0ebf35,0xbd493f78bf753dc9,0x3f5c3f2cbe483f6d,0xbeacbf7d3f46bef1,0x3e16bf713f7b0000,0xbf3e3f04bf62bf22,0x3e793f80bf553ec4,0x3edbbf4e3f7f3e95,
0x3f4ebedb3f553f35,0xbf80be79be95bf7f,0xbf043f3ebf7bbec4,0x3f71be163f223f62,0x3f7d3eac3e483f80,0xbf2cbf5c3ef1bf46,0xbf783d49bf0ebf6d,0x3f673f18bdc93f75,
0xbee63f58bf7fbe48,0x3f6fbe893f2c3f4e,0x3f1dbf393f753ec4,0xbf7c3d97bf04bf67,0xbf423f13bf62bf0e,0x3f803dfb3eac3f78,0x3f5fbecf3f463f35,0xbf7abea1be16bf80,
0xbf65bf093dc9bf7b,0x3eb83f77bf3e3f18,0x3f4a3f31be953f6d,0xbe2fbf7f3f5cbedb,0xbf27bf513ef1bf55,0xbcc93f7ebf713e79,0x3efc3f6abf223f35,0x3e60bf733f7dbd49,
0x3f6d3ec400003f80,0xbec4bf6d3f35bf35,0xbf6dbec40000bf80,0x3ec43f6dbf353f35,0x3f6d3ec400003f80,0xbec4bf6d3f35bf35,0xbf6dbec40000bf80,0x3ec43f6dbf353f35,
0xbec43f6dbf808000,0x3f6dbec43f353f35,0x3ec4bf6d3f808000,0xbf6d3ec4bf35bf35,0xbec43f6dbf808000,0x3f6dbec43f353f35,0x3ec4bf6d3f808000,0xbf6d3ec4bf35bf35,
0xbd97bf7c3f62bf0e,0xbf313f4abf71be79,0x3e893f6fbf463f35,0x3f09bf653f7d3d49,0x3ea1bf7a3f7fbe48,0xbf6a3efcbf3ebf18,0xbdfb3f80bf753ec4,0x3f51bf273f5c3edb,
0x3f7fbe2f3ef13f55,0xbf39bf1d3eacbf78,0xbf773eb8bf22bf35,0x3f583ee6be163f80,0x3f733e603dc93f7b,0xbecfbf5f3f2cbf4e,0xbf7ebcc9be95bf6d,0x3f133f42bf043f67,
0xbf7d3eacbf0ebf35,0x3f3e3f04be953f7f,0x3f783d493e483f6d,0xbedbbf4e3f22bf62,0xbf183f67bf7b0000,0x3f80be793ef13f46,0x3f5cbf2c3f553ec4,0xbf71be16bdc9bf75,
0xbe16bf713f55bf35,0xbf2c3f5cbf75bdc9,0xbe793f80bf7b3ec4,0x3f67bf183f463ef1,0xbf4ebedb3e48bf80,0x3d493f78bf623f22,0x3f043f3ebf0e3f6d,0x3eacbf7d3f7fbe95,
0xbe2f3f7ebf753f0e,0x3f65bf313f4e3eac,0xbecfbf423f22bf6d,0xbefc3f7abf803e79,0x3f583e89bdc93f7b,0xbd97bf6f3f5cbf3e,0xbf803ea1bef1bf35,0x3f1d3f13bedb3f7d,
0xbf7c3dfbbe95bf55,0x3ee63f39bf183f71,0x3f6abf273f463ec4,0xbf5fbe603d49bf78,0xbf093f77bf7f3e48,0x3f7fbeb83f043f2c,0xbcc9bf733f62bf35,0xbf4a3f51bf67be16,
0xbf22bef13ec4bf80,0xbe953f7fbf7b3f0e,0xbdc93f75bf6d3f35,0x3f62bf463f553e48,0x3f46bf623f6d0000,0xbf753dc9be48bf55,0xbf7f3e95bec4bf35,0x3ef13f22bf0e3f7b,
0x3f46bf623f6d8000,0xbf753dc9be48bf55,0xbf7f3e95bec4bf35,0x3ef13f22bf0e3f7b,0x3f223ef1bec43f80,0x3e95bf7f3f7bbf0e,0x3dc9bf753f6dbf35,0xbf623f46bf55be48,
0xbf6f3f42bf46be48,0x3f4a3e2fbe163f71,0x3e60bf773f75bf35,0xbf733f39bf3ebe79,0x3cc9bf653f62bf55,0xbf5f3f58bf5cbd49,0x3f513dfbbdc93f6d,0x3d97bf6a3f67bf4e,
0xbeb8bf273f22bf7b,0xbf1d3f7cbf7d3eac,0x3f7abe893e953f35,0xbea1bf313f2cbf78,0x3f80bee63ef13f0e,0xbefcbf093f04bf80,0xbf133f7ebf7f3ec4,0x3f7fbecf3edb3f18,
0xbeac3f78bf7b3f35,0x3f7dbf2c3f223e95,0x3f80bf183f0e3ec4,0xbf04bedb3ef1bf7f,0x3f67bf5c3f550000,0xbf4ebd493dc9bf62,0xbf3ebe163e48bf6d,0xbe793f71bf753f46,
0xbf713e79be48bf35,0x3e163f3ebf463f75,0x3d493f4ebf553f6d,0x3f5cbf673f62bdc9,0x3edb3f04bf0e3f80,0x3f18bf803f7fbef1,0x3f2cbf7d3f7bbec4,0xbf783eacbe95bf22,
0x3dfb3f31bf463f7b,0x3f58bf733f67be79,0xbf7f3f13bef1bec4,0x3eb83efcbf183f80,0x3e89bf6a3f75bf55,0xbf7c3f42bf2cbe16,0x3f65be603dc93f35,0x3cc9bf4a3f5cbf71,
0xbf7e3f39bf22be48,0x3f093ea1bedb3f78,0x3d97bf513f62bf6d,0xbf6f3f5fbf4e3d49,0x3f77becf3e953f0e,0xbe2fbf273f3ebf7d,0xbee63f7abf7f3f35,0x3f80bf1d3f043eac,
0x3e483f0ebf353f80,0x3f55bf7b3f6dbec4,0x3f7bbf553f350000,0xbf0ebe483ec4bf6d,0xbe48bf0e3f35bf80,0xbf553f7bbf6d3ec4,0xbf7b3f55bf350000,0x3f0e3e48bec43f6d,
0xbf7b3f55bf358000,0x3f0e3e48bec43f6d,0x3e483f0ebf353f80,0x3f55bf7b3f6dbec4,0x3f7bbf553f358000,0xbf0ebe483ec4bf6d,0xbe48bf0e3f35bf80,0xbf553f7bbf6d3ec4,
0x3f1d3cc9be953f55,0x3f09bf733f80bf4e,0xbf273f7cbf7f3f35,0x3f6fbefc3e793edb,0xbe89becf3f22bf7b,0xbf513f7fbf713f04,0x3f65bf7a3f62bec4,0xbf393dfb3e16bf3e,
0xbf4a3f80bf753f0e,0x3f58bea13d493f18,0xbf423e2f3dc9bf35,0xbeb83f5fbf783f67,0x3f77bf6a3f46be48,0xbf13bd973eacbf5c,0x3ee63e60bef13f6d,0x3f31bf7e3f7dbf2c,
0x3f2cbe16be483f35,0x3f04bf673f7fbf62,0x3f71bf783f55bec4,0xbf183d493e95bf46,0xbf803f4ebf0e0000,0x3e793eacbf223f75,0xbedb3f5cbf7b3f6d,0x3f7dbf3e3ef13dc9,
0xbf3e3f7dbf7b3f35,0x3f5cbedb3dc93ef1,0x3eac3e79bf0e3f6d,0x3f4ebf803f75bf22,0x3d49bf183f55bf80,0xbf783f71bf463e95,0xbf673f04be48bec4,0xbe163f2cbf623f7f,
0x3ecf3d97bef13f55,0x3f4abf7c3f78bf3e,0xbf093f5fbf7f3f6d,0x3f73bf313eac3e16,0xbf803f65bf223e48,0x3e893e60bf183f67,0xbf133dfb3e95bf35,0xbf273f6fbf803f5c,
0xbf6a3f7fbf623f0e,0x3f1dbe2fbe793f2c,0xbf583efcbdc9bec4,0xbea13f39bf713f7d,0xbcc9bee63f46bf7b,0xbf773f7abf4e3edb,0x3f51bf7e3f75bf35,0xbf423eb83d49bf04,
0x3e95bf223f6dbf80,0xbf7f3f62bf0e3e48,0xbef13dc93ec4bf35,0xbf463f75bf7b3f55,0xbf753f46bec40000,0xbdc93ef1bf553f7b,0xbf623f7fbf6d3f35,0x3f22be95be483f0e,
0x3f75bf463ec48000,0x3dc9bef13f55bf7b,0x3f62bf7f3f6dbf35,0xbf223e953e48bf0e,0x3e95bf223f6dbf80,0xbf7f3f62bf0e3e48,0xbef13dc93ec4bf35,0xbf463f75bf7b3f55,
0x3f13bf4a3f7fbf7b,0xbf653f39be79bd49,0x3f6fbf7f3f62bf35,0xbefc3e603eacbf18,0xbf093e893e95bf0e,0xbf423f6abf7d3f67,0x3cc9bea13f46bf6d,0xbf7e3f7cbf3e3f04,
0x3f51bf1d3dc93e48,0x3ee6bf313f78bf80,0x3eb8bd97bef13f35,0x3f5fbf7a3f71bf4e,0x3f58bf773f75bf55,0xbf273ecf3e16bedb,0x3f80bf733f22bec4,0xbdfbbe2f3f2cbf5c,
0x3f78bf803f55bf35,0xbeac3e163ef1bf22,0x3f4ebf673f7bbf6d,0xbf2c3f043dc9be95,0x3f5cbf3e3e480000,0x3edbbf183f75bf7f,0x3f7dbf713f0ebec4,0x3d49be793f46bf62,
0x3e79bd49bf0e3f35,0x3f71bf7d3f62bf46,0x3f18bedbbe483ec4,0x3f3ebf5c3f7fbf75,0xbf043f2cbf7b3f80,0x3f67bf4e3e95bdc9,0xbe163eacbf553f6d,0x3f80bf783f22bef1,
0x3f27bf13bdc93e48,0x3f39bf4a3f80bf7d,0x3efcbecfbe953ec4,0x3f58bf653f78bf71,0x3ea1be60bef13f0e,0x3f6fbf773f67bf5c,0x3dfbbcc9bf223f35,0x3f7cbf7f3f4ebf3e,
0xbf423f51bf7f3f7b,0x3f31bf1dbd493e16,0xbf5f3f6abf753f6d,0x3f09bee6be793eac,0xbf733f7abf623f55,0x3eb8be89bedb3f04,0xbf7e3f80bf463f35,0x3e2fbd97bf183f2c,
0x3f35bf35bf803f80,0xbf353f3500000000,0x3f35bf35bf803f80,0xbf353f3500000000,0x3f35bf35bf803f80,0xbf353f3500000000,0x3f35bf35bf803f80,0xbf353f3500000000,
0x3f35bf3580008000,0x3f35bf35bf803f80,0x3f35bf3580008000,0x3f35bf35bf803f80,0x3f35bf3580008000,0x3f35bf35bf803f80,0x3f35bf3580008000,0x3f35bf35bf803f80,
0x3f733f7abe95be48,0xbf6fbf773eac3e79,0x3f7e3f80bdc90000,0xbf7cbf7f3e163d49,0x3f423f51bf22bf0e,0xbf39bf4a3f2c3f18,0x3f5f3f6abef1bec4,0xbf58bf653f043edb,
0xbea1be60bf75bf7b,0x3eb83e893f713f78,0xbdfbbcc9bf7fbf80,0x3e2f3d973f7d3f80,0xbf27bf13bf46bf55,0x3f313f1d3f3e3f4e,0xbefcbecfbf62bf6d,0x3f093ee63f5c3f67,
0xbf5cbf3ebf0ebf35,0x3f673f4e3ef13f22,0xbf7dbf71be48bec4,0x3f803f783dc93e95,0xbe79bd49bf7bbf80,0x3eac3e163f753f7f,0xbf18bedbbf55bf6d,0x3f2c3f043f463f62,
0xbf04bf2c3f553f35,0x3edb3f18bf62bf46,0xbe16beac3f7b3f6d,0x3d493e79bf7fbf75,0xbf78bf803e488000,0x3f713f7dbe95bdc9,0xbf4ebf673f0e3ec4,0x3f3e3f5cbf22bef1,
0x3f093e893f623f7b,0xbf27becfbf4ebf71,0xbcc9bea13f7f3f6d,0xbdfb3e2fbf80bf78,0xbf13bf4a3f463f0e,0x3ee63f31bf5cbf2c,0xbf6fbf7f3e950000,0x3f5f3f7abedbbe16,
0x3f583f77bef1be48,0xbf42bf6a3f183eac,0x3f803f733dc93ec4,0xbf7ebf7c3d49be79,0x3f513f1d3f223f55,0xbf65bf39bf04bf3e,0x3eb83d973f753f80,0xbefcbe60bf67bf7d,
0x3ef13dc93f6d3f80,0xbf22be95bf55bf7b,0x3f753f463ec43f35,0xbf7fbf62be48bf0e,0x3f623f7fbec40000,0xbf46bf753f0e3e48,0x3e953f22bf6dbf35,0xbdc9bef13f7b3f55,
0x3f623f7fbec48000,0xbf46bf753f0e3e48,0x3e953f22bf6dbf35,0xbdc9bef13f7b3f55,0xbef1bdc9bf6dbf80,0x3f223e953f553f7b,0xbf75bf46bec4bf35,0x3f7f3f623e483f0e,
0xbcc93ee6bf7fbf55,0x3e89be603f7d3f71,0x3f513f7ebef10000,0xbf27bf6f3f2c3e79,0xbf6abf7f3e95be48,0x3f4a3f7cbf04bd49,0xbf58befcbf22bf6d,0x3f733f313edb3f4e,
0xbf80bf65bdc9bf0e,0x3f773f7abe163eac,0xbf13bdfbbf62bf80,0x3f423eb83f3e3f78,0x3ecfbd973f753f7b,0xbf1dbe2fbf5cbf80,0xbf09bf5f3f463ec4,0x3ea13f39bf67bf18,
0xbd49bf183f7b3f35,0xbe793eacbf7fbf62,0x3f673f043f0e3f6d,0xbf7dbf3ebe95bf46,0xbf2cbe16bf55bf80,0x3f5c3edb3f223f75,0xbf71bf783e48bec4,0x3f4e3f80bef13dc9,
0x3f803f4e3e483f35,0xbf78bf713dc9bef1,0x3edb3f5cbf55bec4,0xbe16bf2c3f753f22,0xbf3ebf7d3f0e8000,0x3f043f67bf46be95,0x3eacbe793f7b3f6d,0xbf18bd49bf62bf7f,
0xbe893ecfbf7fbf55,0x3f13bd973f673f78,0x3f653f7abe953ec4,0xbf31bf7e3f18bd49,0x3f1dbcc93f623f7b,0xbf58bea1bf2cbf7d,0xbf27bf7c3f220000,0x3eb83f5fbf5cbeac,
0xbf77bf6a3dc9bf0e,0x3f513f7fbedb3e79,0xbee63e60bf75bf6d,0x3f393dfb3f4e3f80,0x3f4a3f80bef13e48,0xbf09bf733f3e3e16,0x3f423e2f3f463f80,0xbf6fbefcbf04bf71,
0x3f553e483f353f80,0xbf7bbf0ebec4bf6d,0x3f0e3f7bbf350000,0xbe48bf553f6d3ec4,0xbf55be48bf35bf80,0x3f7b3f0e3ec43f6d,0xbf0ebf7b3f350000,0x3e483f55bf6dbec4,
0x3f0e3f7bbf358000,0xbe48bf553f6d3ec4,0xbf55be48bf35bf80,0x3f7b3f0e3ec43f6d,0xbf0ebf7b3f358000,0x3e483f55bf6dbec4,0x3f553e483f353f80,0xbf7bbf0ebec4bf6d,
0xbf77becfbef1bf7b,0x3f7c3f423d493f4e,0x3ee63f7abf460000,0xbcc9bf4a3f783edb,0x3f7e3f393dc93f55,0xbf58bf733eacbf04,0xbd97bf513f753ec4,0xbeb83efcbf7dbf3e,
0xbe89bf6a3f623e48,0xbe2f3f27bf80bf18,0xbf65be60bf22bf80,0x3f803f1d3e793f67,0xbdfb3f31bf7fbf0e,0x3f09bea13f713f5c,0x3f7f3f133e953f6d,0xbf6fbf5f3e16bf2c,
0x3f673f5cbe483f35,0xbf18bf803f22be95,0xbf3e3e16bf55bf6d,0x3f783eac3ef13f7f,0xbf71be79bf0ebf80,0x3f7d3f2c3dc93f62,0x3d49bf4e3f7b3ec4,0xbf043edbbf75bf46,
0xbedb3f04bf7bbf35,0x3f4ebd493f463f75,0xbf2cbf7d3f0ebec4,0x3e793f71bf62bdc9,0xbeacbf783f558000,0xbe163f3ebf7fbef1,0x3f803f183e483f6d,0xbf5cbf673e95bf22,
0xbcc9bf653f753e48,0xbefc3f09bf78bf2c,0xbf513dfbbf46bf6d,0x3f7f3ecf3eac3f7d,0x3f6f3f42bdc93f55,0xbf1dbf7c3f18bedb,0xbe60bf773f620000,0xbea13f31bf80bf04,
0x3f803ee63e953f7b,0xbf5fbf583e79bf3e,0xbf13bf7e3f22bec4,0x3d973f6abf71be16,0xbeb83f27bf7fbf0e,0x3f4abe2f3f4e3f67,0x3f7a3e893ef13f80,0xbf73bf393d49bf5c,
0x3f7f3e953ec43f80,0xbf62bf463e48bf55,0xbf223ef1bf6dbf35,0x3f753dc93f0e3f7b,0xbdc9bf753f6d0000,0xbef13f22bf7bbf0e,0x3f463f62bec43f35,0xbe95bf7f3f55be48,
0x3dc93f75bf6d8000,0x3ef1bf223f7b3f0e,0xbf46bf623ec4bf35,0x3e953f7fbf553e48,0x3f7f3e953ec43f80,0xbf62bf463e48bf55,0xbf223ef1bf6dbf35,0x3f753dc93f0e3f7b,
0xbf09bf773f22bf0e,0xbd973f6fbf78bd49,0xbcc93f73bf750000,0x3f1dbf133f713f18,0xbf7cbdfbbef1bf7b,0x3f653f31be163f67,0x3f6a3f27bdc93f6d,0xbefcbf7a3f2cbf04,
0x3f58be893f463f55,0xbf7fbeb8be79bf80,0xbf80bea1be95bf80,0x3f4a3f51beac3f4e,0xbe2fbf7e3f62be48,0xbee63f39bf7dbedb,0xbecf3f42bf7fbec4,0x3f5fbe603f3e3f5c,
0xbf4e3edbbf55bf35,0x3f803e793e953f7f,0x3f04bf3e3f7b3ec4,0xbf713e16bf22bf62,0xbf7dbeacbe48bf80,0x3f2c3f5cbef13f46,0x3f78bd493f0e3f6d,0xbf67bf183dc9bf75,
0xbf18bf673f0ebf35,0xbd493f78bf753dc9,0x3f5c3f2cbe483f6d,0xbeacbf7d3f46bef1,0x3e16bf713f7b8000,0xbf3e3f04bf62bf22,0x3e793f80bf553ec4,0x3edbbf4e3f7f3e95,
0x3ea13f7abf463f0e,0x3ecfbf5f3f803e16,0xbdfbbf803f62bec4,0xbf133f42bf78beac,0xbd973f7cbf753e48,0x3f39bf1d3f673f04,0x3e89bf6f3f7f0000,0xbf583ee6bf4ebf2c,
0xbf733e60bf22bf55,0x3f6a3efcbd493f7d,0x3f7ebcc93ef13f6d,0xbf51bf273e79bf71,0xbf7fbe2fbe95bf7b,0x3f313f4abedb3f5c,0x3f773eb83dc93f80,0xbf09bf653f18bf3e,
0x3f6d3ec400003f80,0xbec4bf6d3f35bf35,0xbf6dbec40000bf80,0x3ec43f6dbf353f35,0x3f6d3ec400003f80,0xbec4bf6d3f35bf35,0xbf6dbec40000bf80,0x3ec43f6dbf353f35,
0xbec43f6dbf808000,0x3f6dbec43f353f35,0x3ec4bf6d3f808000,0xbf6d3ec4bf35bf35,0xbec43f6dbf808000,0x3f6dbec43f353f35,0x3ec4bf6d3f808000,0xbf6d3ec4bf35bf35,
0x3f27bf513f753e48,0xbf803dfbbedbbf5c,0xbefc3f6abf7f0000,0x3f7abea13f183f3e,0x3f65bf093f463f0e,0xbf6fbe89bd49bf7d,0xbf4a3f31bf62bec4,0x3f7c3d973e793f71,
0x3f423f13be953f7b,0xbcc9bf7e3f67bf04,0xbf5fbecf3dc9bf80,0x3e603f73bf4e3f2c,0x3ee63f58bf223f55,0x3eb8bf773f80be16,0xbf1dbf393ef1bf6d,0xbe2f3f7fbf783eac,
0xbe16bf713f55bf35,0xbf2c3f5cbf75bdc9,0xbe793f80bf7b3ec4,0x3f67bf183f463ef1,0xbf4ebedb3e48bf80,0x3d493f78bf623f22,0x3f043f3ebf0e3f6d,0x3eacbf7d3f7fbe95,
0x3f7dbeac3f0e3f35,0xbf3ebf043e95bf7f,0xbf78bd49be48bf6d,0x3edb3f4ebf223f62,0x3f18bf673f7b8000,0xbf803e79bef1bf46,0xbf5c3f2cbf55bec4,0x3f713e163dc93f75,
0xbf13bf1d3ef1bf7b,0xbea13f80bf7d3edb,0x3f6f3d973dc93f6d,0xbe89bf583f3ebf5c,0xbf7a3efcbf22bf0e,0x3f423ecfbe793f80,0x3f31bf653f750000,0xbf7e3e2fbeacbf4e,
0x3f51bf4a3f623e48,0xbf73bcc9be16bf67,0xbeb83f7fbf7f3ec4,0x3f77bf093f2c3f04,0xbe60bf5f3f46bf55,0xbf273f6abf783d49,0x3f393ee6be953f80,0x3dfbbf7c3f71bf18,
0x3f223ef1bec43f80,0x3e95bf7f3f7bbf0e,0x3dc9bf753f6dbf35,0xbf623f46bf55be48,0xbf463f62bf6d0000,0x3f75bdc93e483f55,0x3f7fbe953ec43f35,0xbef1bf223f0ebf7b,
0xbf463f62bf6d8000,0x3f75bdc93e483f55,0x3f7fbe953ec43f35,0xbef1bf223f0ebf7b,0xbf22bef13ec4bf80,0xbe953f7fbf7b3f0e,0xbdc93f75bf6d3f35,0x3f62bf463f553e48,
0x3f6abd973dc93f55,0xbdfbbf513f4ebf67,0xbf583f5fbf620000,0x3f65bcc93d493f5c,0xbf393f73bf753e48,0x3f77be603e793f3e,0xbe2fbf4a3f46bf6d,0xbf423f6fbf713e16,
0xbecf3f7fbf7f3f0e,0x3f7ebf133f183edb,0xbf09befc3ef1bf80,0xbee63f80bf803f04,0xbf31bea13e95bf7b,0xbe893f7abf783f2c,0x3f7cbf1d3f223ec4,0xbf27beb83eacbf7d,
0x3f71be793e483f35,0xbe16bf3e3f46bf75,0xbd49bf4e3f55bf6d,0xbf5c3f67bf623dc9,0xbedbbf043f0ebf80,0xbf183f80bf7f3ef1,0xbf2c3f7dbf7b3ec4,0x3f78beac3e953f22,
0xbeac3f78bf7b3f35,0x3f7dbf2c3f223e95,0x3f80bf183f0e3ec4,0xbf04bedb3ef1bf7f,0x3f67bf5c3f558000,0xbf4ebd493dc9bf62,0xbf3ebe163e48bf6d,0xbe793f71bf753f46,
0x3f4abcc9bdc93f55,0x3e60bf653f71bf5c,0xbf423f7cbf753ec4,0x3f6abe893e163f2c,0xbefcbeb83ef1bf7b,0xbf133f7fbf803f18,0x3f73bf583f460000,0xbf31bdfb3e79bf67,
0xbf1d3f80bf7f3f0e,0x3f7abee63eac3f04,0xbf27be2f3e95bf6d,0xbecf3f77bf7d3f3e,0x3f5fbf6f3f62be48,0xbf513d973d49bf4e,0x3ea13f09bf223f80,0x3f39bf7e3f78bedb,
0x3e483f0ebf353f80,0x3f55bf7b3f6dbec4,0x3f7bbf553f350000,0xbf0ebe483ec4bf6d,0xbe48bf0e3f35bf80,0xbf553f7bbf6d3ec4,0xbf7b3f55bf350000,0x3f0e3e48bec43f6d,
0xbf7b3f55bf358000,0x3f0e3e48bec43f6d,0x3e483f0ebf353f80,0x3f55bf7b3f6dbec4,0x3f7bbf553f358000,0xbf0ebe483ec4bf6d,0xbe48bf0e3f35bf80,0xbf553f7bbf6d3ec4,
0xbdfb3f39bf623f7b,0x3f7abf653f3ebe16,0xbf7f3f51bf220000,0x3ecf3e89bf043f71,0x3efcbf6f3f7fbf55,0xbf7c3f27bedbbe79,0x3f73bf093e953ec4,0xbcc9bf1d3f4ebf80,
0xbf7e3f31bef1be48,0x3e603ee6bf2c3f7d,0xbd97bf133f46bf80,0xbf6a3f77bf5c3eac,0x3f5fbeb83dc93f0e,0x3e2fbf423f67bf78,0xbea13f58bf753f6d,0x3f80bf4a3f183d49,
0xbf3e3f7dbf7b3f35,0x3f5cbedb3dc93ef1,0x3eac3e79bf0e3f6d,0x3f4ebf803f75bf22,0x3d49bf183f55bf80,0xbf783f71bf463e95,0xbf673f04be48bec4,0xbe163f2cbf623f7f,
0xbf2c3e163e48bf35,0xbf043f67bf7f3f62,0xbf713f78bf553ec4,0x3f18bd49be953f46,0x3f80bf4e3f0e8000,0xbe79beac3f22bf75,0x3edbbf5c3f7bbf6d,0xbf7d3f3ebef1bdc9,
0xbf6f3f27be95be48,0xbdfb3f13bf5c3f80,0xbe60be893f22bf6d,0xbf653f80bf673f18,0x3f31bf733f7fbf55,0xbf5f3f09be16beac,0x3f7cbf4a3ef10000,0xbd97becf3f3ebf78,
0x3eb8bf423f75bf7b,0xbf7e3f51bf043d49,0x3f7abf773f46bec4,0xbee6bcc93edbbf4e,0x3f39bea1bdc93f0e,0x3efcbf583f7dbf71,0xbe2f3f1dbf623f80,0x3f7fbf6a3f2cbe79,
0xbe953f22bf6d3f80,0x3f7fbf623f0ebe48,0x3ef1bdc9bec43f35,0x3f46bf753f7bbf55,0x3f75bf463ec40000,0x3dc9bef13f55bf7b,0x3f62bf7f3f6dbf35,0xbf223e953e48bf0e,
0xbf753f46bec48000,0xbdc93ef1bf553f7b,0xbf623f7fbf6d3f35,0x3f22be95be483f0e,0xbe953f22bf6d3f80,0x3f7fbf623f0ebe48,0x3ef1bdc9bec43f35,0x3f46bf753f7bbf55,
0xbf7c3f7ebf463f0e,0x3ea1bcc9bf043f3e,0xbf6a3f42be950000,0xbe893f09bf673f7d,0xbe603efcbf623f7b,0x3f7fbf6f3f18beac,0xbf393f65bf7f3f6d,0x3f4abf133d493e79,
0xbe2fbdfb3f22bf55,0xbf733f80bf5c3f2c,0x3ecfbf273f75bf80,0xbf773f58bedb3e16,0xbf7a3f5fbef13e48,0xbd973eb8bf4e3f71,0xbf313ee63dc9bec4,0xbf1d3f51bf803f78,
0xbe793d493f0ebf35,0xbf713f7dbf623f46,0xbf183edb3e48bec4,0xbf3e3f5cbf7f3f75,0x3f04bf2c3f7bbf80,0xbf673f4ebe953dc9,0x3e16beac3f55bf6d,0xbf803f78bf223ef1,
0x3f78bf803f55bf35,0xbeac3e163ef1bf22,0x3f4ebf673f7bbf6d,0xbf2c3f043dc9be95,0x3f5cbf3e3e488000,0x3edbbf183f75bf7f,0x3f7dbf713f0ebec4,0x3d49be793f46bf62,
0x3f7fbf7c3f22bf0e,0x3cc9bdfb3f3ebf4e,0x3f77bf6f3ef1bec4,0x3e60bea13f5cbf67,0x3f65bf583e95be48,0x3ecfbefc3f71bf78,0x3f4abf393dc90000,0x3f13bf273f7dbf80,
0xbd973e2fbf463f55,0x3f80bf7e3f2cbf18,0xbe893eb8bf623f6d,0x3f7abf733f04bedb,0xbee63f09bf753f7b,0x3f6abf5f3eacbe79,0xbf1d3f31bf7f3f80,0x3f51bf423e16bd49,
0x3f35bf35bf803f80,0xbf353f3500000000,0x3f35bf35bf803f80,0xbf353f3500000000,0x3f35bf35bf803f80,0xbf353f3500000000,0x3f35bf35bf803f80,0xbf353f3500000000,
0x3f35bf3580008000,0x3f35bf35bf803f80,0x3f35bf3580008000,0x3f35bf35bf803f80,0x3f35bf3580008000,0x3f35bf35bf803f80,0x3f35bf3580008000,0x3f35bf35bf803f80,
0x3ee63f09bf62bf55,0xbecfbefc3f673f5c,0x3f1d3f31bf46bf35,0xbf13bf273f4e3f3e,0x3d973e2fbf7fbf7b,0xbcc9bdfb3f803f7d,0x3e893eb8bf75bf6d,0xbe60bea13f783f71,
0xbf65bf58bef1bf0e,0x3f6a3f5f3edb3f04,0xbf4abf39bf22bf35,0x3f513f423f183f2c,0xbf7fbf7cbdc9be48,0x3f803f7e3d493e16,0xbf77bf6fbe95bec4,0x3f7a3f733e793eac,
0xbf04bf2c3f553f35,0x3edb3f18bf62bf46,0xbe16beac3f7b3f6d,0x3d493e79bf7fbf75,0xbf78bf803e480000,0x3f713f7dbe95bdc9,0xbf4ebf673f0e3ec4,0x3f3e3f5cbf22bef1,
0x3f5c3f3e3f0e3f35,0xbf67bf4ebef1bf22,0x3f7d3f713e483ec4,0xbf80bf78bdc9be95,0x3e793d493f7b3f80,0xbeacbe16bf75bf7f,0x3f183edb3f553f6d,0xbf2cbf04bf46bf62,
0x3e603efcbf75bf55,0xbd97beb83f7d3f67,0x3f393f65bf22bec4,0xbf1dbf513f3e3f04,0x3f7c3f7ebdc93e48,0xbf73bf803e79bd49,0x3f6a3f423ef13f35,0xbf77bf58beacbf18,
0xbf7abf5fbe95bf0e,0x3f7f3f6f3e163edb,0xbf31bee6bf46bf6d,0x3f4a3f133f2c3f5c,0xbe2f3dfbbf7fbf7b,0x3ea13cc93f783f80,0x3ecf3f27bf62bf35,0xbe89bf093f713f4e,
0xbef1bdc9bf6dbf80,0x3f223e953f553f7b,0xbf75bf46bec4bf35,0x3f7f3f623e483f0e,0xbf62bf7f3ec40000,0x3f463f75bf0ebe48,0xbe95bf223f6d3f35,0x3dc93ef1bf7bbf55,
0xbf62bf7f3ec48000,0x3f463f75bf0ebe48,0xbe95bf223f6d3f35,0x3dc93ef1bf7bbf55,0x3ef13dc93f6d3f80,0xbf22be95bf55bf7b,0x3f753f463ec43f35,0xbf7fbf62be48bf0e,
0x3f393ea13f463f7b,0xbf5fbf09bf18bf67,0xbe2fbf1d3f753f35,0xbd973ecfbf80bf5c,0x3eb83f42bf62bf0e,0xbdfbbf133f783f3e,0x3f7a3f77bdc93ec4,0xbf65bf803eacbe16,
0x3f313f73bf22be48,0xbefcbf583f4e3edb,0x3f7c3f4a3e953f35,0xbf7fbf6abd49bf04,0xbf6fbf27bef1bf55,0x3f7e3f513e793f2c,0xbe603e89bf7fbf6d,0x3ee6bcc93f713f7d,
0xbf80bf4ebe48bf35,0x3f783f71bdc93ef1,0xbedbbf5c3f553ec4,0x3e163f2cbf75bf22,0x3f3e3f7dbf0e0000,0xbf04bf673f463e95,0xbeac3e79bf7bbf6d,0x3f183d493f623f7f,
0xbd49bf183f7b3f35,0xbe793eacbf7fbf62,0x3f673f043f0e3f6d,0xbf7dbf3ebe95bf46,0xbf2cbe16bf55bf80,0x3f5c3edb3f223f75,0xbf71bf783e48bec4,0x3f4e3f80bef13dc9,
0x3efc3f6fbf46be48,0xbe2fbf423f713f04,0x3f733f093ef13f6d,0xbf80bf4abe16bf3e,0xbdfbbf393f753f0e,0xbe603ee6bf80bf4e,0xbf7fbf51bdc9bf35,0x3f6a3f77be793edb,
0xbf5fbeb8bf22bf7b,0x3f7c3f273eac3f5c,0x3ea13f58bf62bec4,0x3cc9bf1d3f7d3f2c,0x3f7e3f313e953f55,0xbf7abf653d49bf18,0x3d97bf133f7f3f35,0xbecf3e89bf78bf67,
0x3f553e483f353f80,0xbf7bbf0ebec4bf6d,0x3f0e3f7bbf350000,0xbe48bf553f6d3ec4,0xbf55be48bf35bf80,0x3f7b3f0e3ec43f6d,0xbf0ebf7b3f350000,0x3e483f55bf6dbec4,
0x3f0e3f7bbf358000,0xbe48bf553f6d3ec4,0xbf55be48bf35bf80,0x3f7b3f0e3ec43f6d,0xbf0ebf7b3f358000,0x3e483f55bf6dbec4,0x3f553e483f353f80,0xbf7bbf0ebec4bf6d,
0xbf5fbf6f3e95bf0e,0x3f133f7fbf2c3e16,0xbea13f09bf7fbf35,0x3f31bdfb3f5c3f71,0x3f1d3f80bf223e48,0xbe60bf653f673e79,0x3f27be2f3f623f6d,0xbf6abe89bf18bf80,
0x3efcbeb83f753f55,0xbf51bd97bf3ebf7d,0xbf73bf583dc9bf35,0x3f393f7ebf043eac,0xbf4abcc9bf46bf7b,0x3f7a3ee63edb3f78,0x3f423f7cbef13ec4,0xbecfbf773f4e3d49,
0xbedb3f04bf7bbf35,0x3f4ebd493f463f75,0xbf2cbf7d3f0ebec4,0x3e793f71bf62bdc9,0xbeacbf783f550000,0xbe163f3ebf7fbef1,0x3f803f183e483f6d,0xbf5cbf673e95bf22,
0xbf67bf5c3e48bf35,0x3f183f80bf223e95,0x3f3ebe163f553f6d,0xbf78beacbef1bf7f,0x3f713e793f0e3f80,0xbf7dbf2cbdc9bf62,0xbd493f4ebf7bbec4,0x3f04bedb3f753f46,
0x3f393f73bef13f0e,0xbe89bf7a3f5cbd49,0x3e2fbf4a3f7f3ec4,0xbf273eb8bf67bf4e,0xbf6abd97bf22bf7b,0x3f7e3f133e163f71,0x3f583f5fbe953f35,0xbee6bf803f3ebe79,
0xbf313ea1bf62bf55,0x3f773e603f043f80,0x3f7c3f1d3dc93f6d,0xbf42bf6f3edbbf18,0xbecfbf7f3f46be48,0xbdfb3f51bf7dbeac,0xbf093efcbf75bf35,0x3f653cc93f2c3f78,
0xbf7fbe95bec4bf80,0x3f623f46be483f55,0x3f22bef13f6d3f35,0xbf75bdc9bf0ebf7b,0x3dc93f75bf6d0000,0x3ef1bf223f7b3f0e,0xbf46bf623ec4bf35,0x3e953f7fbf553e48,
0xbdc9bf753f6d8000,0xbef13f22bf7bbf0e,0x3f463f62bec43f35,0xbe95bf7f3f55be48,0xbf7fbe95bec4bf80,0x3f623f46be483f55,0x3f22bef13f6d3f35,0xbf75bdc9bf0ebf7b,
0xbe603f5fbf7fbe48,0x3f42becf3f5c3f3e,0x3f39bee63f623f35,0xbf7ebe2fbedbbf7d,0x3f513f4abe953f55,0xbea1bf803f4ebeac,0xbeb8bf7f3f46bec4,0xbe893f58bf80be79,
0xbf7abefcbdc9bf7b,0x3f273f6abf043f2c,0x3f313f65bef13f35,0xbdfbbf7c3f67be16,0xbf133f1dbf75bf0e,0x3f73bcc93f183f71,0x3f6fbd973f223f6d,0xbf77bf09bd49bf78,
0x3f183f67bf0e3f35,0x3d49bf783f75bdc9,0xbf5cbf2c3e48bf6d,0x3eac3f7dbf463ef1,0xbe163f71bf7b0000,0x3f3ebf043f623f22,0xbe79bf803f55bec4,0xbedb3f4ebf7fbe95,
0xbf4e3edbbf55bf35,0x3f803e793e953f7f,0x3f04bf3e3f7b3ec4,0xbf713e16bf22bf62,0xbf7dbeacbe48bf80,0x3f2c3f5cbef13f46,0x3f78bd493f0e3f6d,0xbf67bf183dc9bf75,
0x3f653f09bdc93f7b,0xbeb8bf773f3ebf18,0xbf4abf313e95bf6d,0x3e2f3f7fbf5c3edb,0x3f273f51bef13f55,0x3cc9bf7e3f71be79,0xbefcbf6a3f22bf35,0xbe603f73bf7d3d49,
0xbee63f58bf7fbe48,0x3f6fbe893f2c3f4e,0x3f1dbf393f753ec4,0xbf7c3d97bf04bf67,0xbf423f13bf62bf0e,0x3f803dfb3eac3f78,0x3f5fbecf3f463f35,0xbf7abea1be16bf80,
0x3f6d3ec400003f80,0xbec4bf6d3f35bf35,0xbf6dbec40000bf80,0x3ec43f6dbf353f35,0x3f6d3ec400003f80,0xbec4bf6d3f35bf35,0xbf6dbec40000bf80,0x3ec43f6dbf353f35,
0xbec43f6dbf808000,0x3f6dbec43f353f35,0x3ec4bf6d3f808000,0xbf6d3ec4bf35bf35,0xbec43f6dbf808000,0x3f6dbec43f353f35,0x3ec4bf6d3f808000,0xbf6d3ec4bf35bf35,
0x3f7fbe2f3ef13f55,0xbf39bf1d3eacbf78,0xbf773eb8bf22bf35,0x3f583ee6be163f80,0x3f733e603dc93f7b,0xbecfbf5f3f2cbf4e,0xbf7ebcc9be95bf6d,0x3f133f42bf043f67,
0x3d973f7cbf623f0e,0x3f31bf4a3f713e79,0xbe89bf6f3f46bf35,0xbf093f65bf7dbd49,0xbea13f7abf7f3e48,0x3f6abefc3f3e3f18,0x3dfbbf803f75bec4,0xbf513f27bf5cbedb,
0x3f7dbeac3f0e3f35,0xbf3ebf043e95bf7f,0xbf78bd49be48bf6d,0x3edb3f4ebf223f62,0x3f18bf673f7b0000,0xbf803e79bef1bf46,0xbf5c3f2cbf55bec4,0x3f713e163dc93f75,
0x3e163f71bf553f35,0x3f2cbf5c3f753dc9,0x3e79bf803f7bbec4,0xbf673f18bf46bef1,0x3f4e3edbbe483f80,0xbd49bf783f62bf22,0xbf04bf3e3f0ebf6d,0xbeac3f7dbf7f3e95,
0x3f7cbdfb3e953f55,0xbee6bf393f18bf71,0xbf6a3f27bf46bec4,0x3f5f3e60bd493f78,0x3f09bf773f7fbe48,0xbf7f3eb8bf04bf2c,0x3cc93f73bf623f35,0x3f4abf513f673e16,
0xbe2f3f7ebf753f0e,0x3f65bf313f4e3eac,0xbecfbf423f22bf6d,0xbefc3f7abf803e79,0x3f583e89bdc93f7b,0xbd97bf6f3f5cbf3e,0xbf803ea1bef1bf35,0x3f1d3f13bedb3f7d,
0xbf22bef13ec4bf80,0xbe953f7fbf7b3f0e,0xbdc93f75bf6d3f35,0x3f62bf463f553e48,0x3f46bf623f6d0000,0xbf753dc9be48bf55,0xbf7f3e95bec4bf35,0x3ef13f22bf0e3f7b,
0x3f46bf623f6d8000,0xbf753dc9be48bf55,0xbf7f3e95bec4bf35,0x3ef13f22bf0e3f7b,0x3f223ef1bec43f80,0x3e95bf7f3f7bbf0e,0x3dc9bf753f6dbf35,0xbf623f46bf55be48,
0xbeb8bf273f22bf7b,0xbf1d3f7cbf7d3eac,0x3f7abe893e953f35,0xbea1bf313f2cbf78,0x3f80bee63ef13f0e,0xbefcbf093f04bf80,0xbf133f7ebf7f3ec4,0x3f7fbecf3edb3f18,
0x3f6fbf423f463e48,0xbf4abe2f3e16bf71,0xbe603f77bf753f35,0x3f73bf393f3e3e79,0xbcc93f65bf623f55,0x3f5fbf583f5c3d49,0xbf51bdfb3dc9bf6d,0xbd973f6abf673f4e,
0x3eacbf783f7bbf35,0xbf7d3f2cbf22be95,0xbf803f18bf0ebec4,0x3f043edbbef13f7f,0xbf673f5cbf550000,0x3f4e3d49bdc93f62,0x3f3e3e16be483f6d,0x3e79bf713f75bf46,
0x3f71be793e483f35,0xbe16bf3e3f46bf75,0xbd49bf4e3f55bf6d,0xbf5c3f67bf623dc9,0xbedbbf043f0ebf80,0xbf183f80bf7f3ef1,0xbf2c3f7dbf7b3ec4,0x3f78beac3e953f22,
0x3f7ebf393f223e48,0xbf09bea13edbbf78,0xbd973f51bf623f6d,0x3f6fbf5f3f4ebd49,0xbf773ecfbe95bf0e,0x3e2f3f27bf3e3f7d,0x3ee6bf7a3f7fbf35,0xbf803f1dbf04beac,
0x3dfb3f31bf463f7b,0x3f58bf733f67be79,0xbf7f3f13bef1bec4,0x3eb83efcbf183f80,0x3e89bf6a3f75bf55,0xbf7c3f42bf2cbe16,0x3f65be603dc93f35,0x3cc9bf4a3f5cbf71,
0x3e483f0ebf353f80,0x3f55bf7b3f6dbec4,0x3f7bbf553f350000,0xbf0ebe483ec4bf6d,0xbe48bf0e3f35bf80,0xbf553f7bbf6d3ec4,0xbf7b3f55bf350000,0x3f0e3e48bec43f6d,
0xbf7b3f55bf358000,0x3f0e3e48bec43f6d,0x3e483f0ebf353f80,0x3f55bf7b3f6dbec4,0x3f7bbf553f358000,0xbf0ebe483ec4bf6d,0xbe48bf0e3f35bf80,0xbf553f7bbf6d3ec4,
0xbf4a3f80bf753f0e,0x3f58bea13d493f18,0xbf423e2f3dc9bf35,0xbeb83f5fbf783f67,0x3f77bf6a3f46be48,0xbf13bd973eacbf5c,0x3ee63e60bef13f6d,0x3f31bf7e3f7dbf2c,
0xbf1dbcc93e95bf55,0xbf093f73bf803f4e,0x3f27bf7c3f7fbf35,0xbf6f3efcbe79bedb,0x3e893ecfbf223f7b,0x3f51bf7f3f71bf04,0xbf653f7abf623ec4,0x3f39bdfbbe163f3e,
0xbf2c3e163e48bf35,0xbf043f67bf7f3f62,0xbf713f78bf553ec4,0x3f18bd49be953f46,0x3f80bf4e3f0e0000,0xbe79beac3f22bf75,0x3edbbf5c3f7bbf6d,0xbf7d3f3ebef1bdc9,
0x3f3ebf7d3f7bbf35,0xbf5c3edbbdc9bef1,0xbeacbe793f0ebf6d,0xbf4e3f80bf753f22,0xbd493f18bf553f80,0x3f78bf713f46be95,0x3f67bf043e483ec4,0x3e16bf2c3f62bf7f,
0x3f6abf7f3f62bf0e,0xbf1d3e2f3e79bf2c,0x3f58befc3dc93ec4,0x3ea1bf393f71bf7d,0x3cc93ee6bf463f7b,0x3f77bf7a3f4ebedb,0xbf513f7ebf753f35,0x3f42beb8bd493f04,
0x3ecf3d97bef13f55,0x3f4abf7c3f78bf3e,0xbf093f5fbf7f3f6d,0x3f73bf313eac3e16,0xbf803f65bf223e48,0x3e893e60bf183f67,0xbf133dfb3e95bf35,0xbf273f6fbf803f5c,
0x3e95bf223f6dbf80,0xbf7f3f62bf0e3e48,0xbef13dc93ec4bf35,0xbf463f75bf7b3f55,0xbf753f46bec40000,0xbdc93ef1bf553f7b,0xbf623f7fbf6d3f35,0x3f22be95be483f0e,
0x3f75bf463ec48000,0x3dc9bef13f55bf7b,0x3f62bf7f3f6dbf35,0xbf223e953e48bf0e,0x3e95bf223f6dbf80,0xbf7f3f62bf0e3e48,0xbef13dc93ec4bf35,0xbf463f75bf7b3f55,
0x3f51bf1d3dc93e48,0x3ee6bf313f78bf80,0x3eb8bd97bef13f35,0x3f5fbf7a3f71bf4e,0x3f58bf773f75bf55,0xbf273ecf3e16bedb,0x3f80bf733f22bec4,0xbdfbbe2f3f2cbf5c,
0xbf133f4abf7f3f7b,0x3f65bf393e793d49,0xbf6f3f7fbf623f35,0x3efcbe60beac3f18,0x3f09be89be953f0e,0x3f42bf6a3f7dbf67,0xbcc93ea1bf463f6d,0x3f7ebf7c3f3ebf04,
0xbf783f80bf553f35,0x3eacbe16bef13f22,0xbf4e3f67bf7b3f6d,0x3f2cbf04bdc93e95,0xbf5c3f3ebe480000,0xbedb3f18bf753f7f,0xbf7d3f71bf0e3ec4,0xbd493e79bf463f62,
0xbe793d493f0ebf35,0xbf713f7dbf623f46,0xbf183edb3e48bec4,0xbf3e3f5cbf7f3f75,0x3f04bf2c3f7bbf80,0xbf673f4ebe953dc9,0x3e16beac3f55bf6d,0xbf803f78bf223ef1,
0x3f42bf513f7fbf7b,0xbf313f1d3d49be16,0x3f5fbf6a3f75bf6d,0xbf093ee63e79beac,0x3f73bf7a3f62bf55,0xbeb83e893edbbf04,0x3f7ebf803f46bf35,0xbe2f3d973f18bf2c,
0x3f27bf13bdc93e48,0x3f39bf4a3f80bf7d,0x3efcbecfbe953ec4,0x3f58bf653f78bf71,0x3ea1be60bef13f0e,0x3f6fbf773f67bf5c,0x3dfbbcc9bf223f35,0x3f7cbf7f3f4ebf3e,
0x3f35bf35bf803f80,0xbf353f3500000000,0x3f35bf35bf803f80,0xbf353f3500000000,0x3f35bf35bf803f80,0xbf353f3500000000,0x3f35bf35bf803f80,0xbf353f3500000000,
0x3f35bf3580008000,0x3f35bf35bf803f80,0x3f35bf3580008000,0x3f35bf35bf803f80,0x3f35bf3580008000,0x3f35bf35bf803f80,0x3f35bf3580008000,0x3f35bf35bf803f80,
0xbea1be60bf75bf7b,0x3eb83e893f713f78,0xbdfbbcc9bf7fbf80,0x3e2f3d973f7d3f80,0xbf27bf13bf46bf55,0x3f313f1d3f3e3f4e,0xbefcbecfbf62bf6d,0x3f093ee63f5c3f67,
0xbf73bf7a3e953e48,0x3f6f3f77beacbe79,0xbf7ebf803dc98000,0x3f7c3f7fbe16bd49,0xbf42bf513f223f0e,0x3f393f4abf2cbf18,0xbf5fbf6a3ef13ec4,0x3f583f65bf04bedb,
0x3f5c3f3e3f0e3f35,0xbf67bf4ebef1bf22,0x3f7d3f713e483ec4,0xbf80bf78bdc9be95,0x3e793d493f7b3f80,0xbeacbe16bf75bf7f,0x3f183edb3f553f6d,0xbf2cbf04bf46bf62,
0x3f043f2cbf55bf35,0xbedbbf183f623f46,0x3e163eacbf7bbf6d,0xbd49be793f7f3f75,0x3f783f80be488000,0xbf71bf7d3e953dc9,0x3f4e3f67bf0ebec4,0xbf3ebf5c3f223ef1,
0xbf58bf773ef13e48,0x3f423f6abf18beac,0xbf80bf73bdc9bec4,0x3f7e3f7cbd493e79,0xbf51bf1dbf22bf55,0x3f653f393f043f3e,0xbeb8bd97bf75bf80,0x3efc3e603f673f7d,
0x3f093e893f623f7b,0xbf27becfbf4ebf71,0xbcc9bea13f7f3f6d,0xbdfb3e2fbf80bf78,0xbf13bf4a3f463f0e,0x3ee63f31bf5cbf2c,0xbf6fbf7f3e958000,0x3f5f3f7abedbbe16,
0x3ef13dc93f6d3f80,0xbf22be95bf55bf7b,0x3f753f463ec43f35,0xbf7fbf62be48bf0e,0x3f623f7fbec40000,0xbf46bf753f0e3e48,0x3e953f22bf6dbf35,0xbdc9bef13f7b3f55,
0x3f623f7fbec48000,0xbf46bf753f0e3e48,0x3e953f22bf6dbf35,0xbdc9bef13f7b3f55,0xbef1bdc9bf6dbf80,0x3f223e953f553f7b,0xbf75bf46bec4bf35,0x3f7f3f623e483f0e,
0xbf80bf65bdc9bf0e,0x3f773f7abe163eac,0xbf13bdfbbf62bf80,0x3f423eb83f3e3f78,0x3ecfbd973f753f7b,0xbf1dbe2fbf5cbf80,0xbf09bf5f3f463ec4,0x3ea13f39bf67bf18,
0x3cc9bee63f7f3f55,0xbe893e60bf7dbf71,0xbf51bf7e3ef18000,0x3f273f6fbf2cbe79,0x3f6a3f7fbe953e48,0xbf4abf7c3f043d49,0x3f583efc3f223f6d,0xbf73bf31bedbbf4e,
0x3d493f18bf7bbf35,0x3e79beac3f7f3f62,0xbf67bf04bf0ebf6d,0x3f7d3f3e3e953f46,0x3f2c3e163f553f80,0xbf5cbedbbf22bf75,0x3f713f78be483ec4,0xbf4ebf803ef1bdc9,
0xbf80bf4ebe48bf35,0x3f783f71bdc93ef1,0xbedbbf5c3f553ec4,0x3e163f2cbf75bf22,0x3f3e3f7dbf0e8000,0xbf04bf673f463e95,0xbeac3e79bf7bbf6d,0x3f183d493f623f7f,
0x3f773f6abdc93f0e,0xbf51bf7f3edbbe79,0x3ee6be603f753f6d,0xbf39bdfbbf4ebf80,0xbf4abf803ef1be48,0x3f093f73bf3ebe16,0xbf42be2fbf46bf80,0x3f6f3efc3f043f71,
0xbe893ecfbf7fbf55,0x3f13bd973f673f78,0x3f653f7abe953ec4,0xbf31bf7e3f18bd49,0x3f1dbcc93f623f7b,0xbf58bea1bf2cbf7d,0xbf27bf7c3f228000,0x3eb83f5fbf5cbeac,
0x3f553e483f353f80,0xbf7bbf0ebec4bf6d,0x3f0e3f7bbf350000,0xbe48bf553f6d3ec4,0xbf55be48bf35bf80,0x3f7b3f0e3ec43f6d,0xbf0ebf7b3f350000,0x3e483f55bf6dbec4,
0x3f0e3f7bbf358000,0xbe48bf553f6d3ec4,0xbf55be48bf35bf80,0x3f7b3f0e3ec43f6d,0xbf0ebf7b3f358000,0x3e483f55bf6dbec4,0x3f553e483f353f80,0xbf7bbf0ebec4bf6d,
0xbe89bf6a3f623e48,0xbe2f3f27bf80bf18,0xbf65be60bf22bf80,0x3f803f1d3e793f67,0xbdfb3f31bf7fbf0e,0x3f09bea13f713f5c,0x3f7f3f133e953f6d,0xbf6fbf5f3e16bf2c,
0x3f773ecf3ef13f7b,0xbf7cbf42bd49bf4e,0xbee6bf7a3f468000,0x3cc93f4abf78bedb,0xbf7ebf39bdc9bf55,0x3f583f73beac3f04,0x3d973f51bf75bec4,0x3eb8befc3f7d3f3e,
0xbf67bf5c3e48bf35,0x3f183f80bf223e95,0x3f3ebe163f553f6d,0xbf78beacbef1bf7f,0x3f713e793f0e3f80,0xbf7dbf2cbdc9bf62,0xbd493f4ebf7bbec4,0x3f04bedb3f753f46,
0x3edbbf043f7b3f35,0xbf4e3d49bf46bf75,0x3f2c3f7dbf0e3ec4,0xbe79bf713f623dc9,0x3eac3f78bf558000,0x3e16bf3e3f7f3ef1,0xbf80bf18be48bf6d,0x3f5c3f67be953f22,
0xbf80bee6be95bf7b,0x3f5f3f58be793f3e,0x3f133f7ebf223ec4,0xbd97bf6a3f713e16,0x3eb8bf273f7f3f0e,0xbf4a3e2fbf4ebf67,0xbf7abe89bef1bf80,0x3f733f39bd493f5c,
0xbcc9bf653f753e48,0xbefc3f09bf78bf2c,0xbf513dfbbf46bf6d,0x3f7f3ecf3eac3f7d,0x3f6f3f42bdc93f55,0xbf1dbf7c3f18bedb,0xbe60bf773f628000,0xbea13f31bf80bf04,
0x3f7f3e953ec43f80,0xbf62bf463e48bf55,0xbf223ef1bf6dbf35,0x3f753dc93f0e3f7b,0xbdc9bf753f6d0000,0xbef13f22bf7bbf0e,0x3f463f62bec43f35,0xbe95bf7f3f55be48,
0x3dc93f75bf6d8000,0x3ef1bf223f7b3f0e,0xbf46bf623ec4bf35,0x3e953f7fbf553e48,0x3f7f3e953ec43f80,0xbf62bf463e48bf55,0xbf223ef1bf6dbf35,0x3f753dc93f0e3f7b,
0x3f58be893f463f55,0xbf7fbeb8be79bf80,0xbf80bea1be95bf80,0x3f4a3f51beac3f4e,0xbe2fbf7e3f62be48,0xbee63f39bf7dbedb,0xbecf3f42bf7fbec4,0x3f5fbe603f3e3f5c,
0x3f093f77bf223f0e,0x3d97bf6f3f783d49,0x3cc9bf733f758000,0xbf1d3f13bf71bf18,0x3f7c3dfb3ef13f7b,0xbf65bf313e16bf67,0xbf6abf273dc9bf6d,0x3efc3f7abf2c3f04,
0x3f4ebedb3f553f35,0xbf80be79be95bf7f,0xbf043f3ebf7bbec4,0x3f71be163f223f62,0x3f7d3eac3e483f80,0xbf2cbf5c3ef1bf46,0xbf783d49bf0ebf6d,0x3f673f18bdc93f75,
0x3f183f67bf0e3f35,0x3d49bf783f75bdc9,0xbf5cbf2c3e48bf6d,0x3eac3f7dbf463ef1,0xbe163f71bf7b8000,0x3f3ebf043f623f22,0xbe79bf803f55bec4,0xbedb3f4ebf7fbe95,
0x3f73be603f223f55,0xbf6abefc3d49bf7d,0xbf7e3cc9bef1bf6d,0x3f513f27be793f71,0x3f7f3e2f3e953f7b,0xbf31bf4a3edbbf5c,0xbf77beb8bdc9bf80,0x3f093f65bf183f3e,
0x3ea13f7abf463f0e,0x3ecfbf5f3f803e16,0xbdfbbf803f62bec4,0xbf133f42bf78beac,0xbd973f7cbf753e48,0x3f39bf1d3f673f04,0x3e89bf6f3f7f8000,0xbf583ee6bf4ebf2c,
0x3f6d3ec400003f80,0xbec4bf6d3f35bf35,0xbf6dbec40000bf80,0x3ec43f6dbf353f35,0x3f6d3ec400003f80,0xbec4bf6d3f35bf35,0xbf6dbec40000bf80,0x3ec43f6dbf353f35,
0xbec43f6dbf808000,0x3f6dbec43f353f35,0x3ec4bf6d3f808000,0xbf6d3ec4bf35bf35,0xbec43f6dbf808000,0x3f6dbec43f353f35,0x3ec4bf6d3f808000,0xbf6d3ec4bf35bf35,
0x3f423f13be953f7b,0xbcc9bf7e3f67bf04,0xbf5fbecf3dc9bf80,0x3e603f73bf4e3f2c,0x3ee63f58bf223f55,0x3eb8bf773f80be16,0xbf1dbf393ef1bf6d,0xbe2f3f7fbf783eac,
0xbf273f51bf75be48,0x3f80bdfb3edb3f5c,0x3efcbf6a3f7f8000,0xbf7a3ea1bf18bf3e,0xbf653f09bf46bf0e,0x3f6f3e893d493f7d,0x3f4abf313f623ec4,0xbf7cbd97be79bf71,
0x3e163f71bf553f35,0x3f2cbf5c3f753dc9,0x3e79bf803f7bbec4,0xbf673f18bf46bef1,0x3f4e3edbbe483f80,0xbd49bf783f62bf22,0xbf04bf3e3f0ebf6d,0xbeac3f7dbf7f3e95,
0xbf7d3eacbf0ebf35,0x3f3e3f04be953f7f,0x3f783d493e483f6d,0xbedbbf4e3f22bf62,0xbf183f67bf7b8000,0x3f80be793ef13f46,0x3f5cbf2c3f553ec4,0xbf71be16bdc9bf75,
0xbf513f4abf62be48,0x3f733cc93e163f67,0x3eb8bf7f3f7fbec4,0xbf773f09bf2cbf04,0x3e603f5fbf463f55,0x3f27bf6a3f78bd49,0xbf39bee63e95bf80,0xbdfb3f7cbf713f18,
0xbf13bf1d3ef1bf7b,0xbea13f80bf7d3edb,0x3f6f3d973dc93f6d,0xbe89bf583f3ebf5c,0xbf7a3efcbf22bf0e,0x3f423ecfbe793f80,0x3f31bf653f758000,0xbf7e3e2fbeacbf4e,
0x3f223ef1bec43f80,0x3e95bf7f3f7bbf0e,0x3dc9bf753f6dbf35,0xbf623f46bf55be48,0xbf463f62bf6d0000,0x3f75bdc93e483f55,0x3f7fbe953ec43f35,0xbef1bf223f0ebf7b,
0xbf463f62bf6d8000,0x3f75bdc93e483f55,0x3f7fbe953ec43f35,0xbef1bf223f0ebf7b,0xbf22bef13ec4bf80,0xbe953f7fbf7b3f0e,0xbdc93f75bf6d3f35,0x3f62bf463f553e48,
0xbecf3f7fbf7f3f0e,0x3f7ebf133f183edb,0xbf09befc3ef1bf80,0xbee63f80bf803f04,0xbf31bea13e95bf7b,0xbe893f7abf783f2c,0x3f7cbf1d3f223ec4,0xbf27beb83eacbf7d,
0xbf6a3d97bdc9bf55,0x3dfb3f51bf4e3f67,0x3f58bf5f3f628000,0xbf653cc9bd49bf5c,0x3f39bf733f75be48,0xbf773e60be79bf3e,0x3e2f3f4abf463f6d,0x3f42bf6f3f71be16,
0xbf713e79be48bf35,0x3e163f3ebf463f75,0x3d493f4ebf553f6d,0x3f5cbf673f62bdc9,0x3edb3f04bf0e3f80,0x3f18bf803f7fbef1,0x3f2cbf7d3f7bbec4,0xbf783eacbe95bf22,
0x3eacbf783f7bbf35,0xbf7d3f2cbf22be95,0xbf803f18bf0ebec4,0x3f043edbbef13f7f,0xbf673f5cbf558000,0x3f4e3d49bdc93f62,0x3f3e3e16be483f6d,0x3e79bf713f75bf46,
0x3f1dbf803f7fbf0e,0xbf7a3ee6beacbf04,0x3f273e2fbe953f6d,0x3ecfbf773f7dbf3e,0xbf5f3f6fbf623e48,0x3f51bd97bd493f4e,0xbea1bf093f22bf80,0xbf393f7ebf783edb,
0x3f4abcc9bdc93f55,0x3e60bf653f71bf5c,0xbf423f7cbf753ec4,0x3f6abe893e163f2c,0xbefcbeb83ef1bf7b,0xbf133f7fbf803f18,0x3f73bf583f468000,0xbf31bdfb3e79bf67,
0x3e483f0ebf353f80,0x3f55bf7b3f6dbec4,0x3f7bbf553f350000,0xbf0ebe483ec4bf6d,0xbe48bf0e3f35bf80,0xbf553f7bbf6d3ec4,0xbf7b3f55bf350000,0x3f0e3e48bec43f6d,
0xbf7b3f55bf358000,0x3f0e3e48bec43f6d,0x3e483f0ebf353f80,0x3f55bf7b3f6dbec4,0x3f7bbf553f358000,0xbf0ebe483ec4bf6d,0xbe48bf0e3f35bf80,0xbf553f7bbf6d3ec4,
0xbf7e3f31bef1be48,0x3e603ee6bf2c3f7d,0xbd97bf133f46bf80,0xbf6a3f77bf5c3eac,0x3f5fbeb83dc93f0e,0x3e2fbf423f67bf78,0xbea13f58bf753f6d,0x3f80bf4a3f183d49,
0x3dfbbf393f62bf7b,0xbf7a3f65bf3e3e16,0x3f7fbf513f228000,0xbecfbe893f04bf71,0xbefc3f6fbf7f3f55,0x3f7cbf273edb3e79,0xbf733f09be95bec4,0x3cc93f1dbf4e3f80,
0x3f3ebf7d3f7bbf35,0xbf5c3edbbdc9bef1,0xbeacbe793f0ebf6d,0xbf4e3f80bf753f22,0xbd493f18bf553f80,0x3f78bf713f46be95,0x3f67bf043e483ec4,0x3e16bf2c3f62bf7f,
0x3f2cbe16be483f35,0x3f04bf673f7fbf62,0x3f71bf783f55bec4,0xbf183d493e95bf46,0xbf803f4ebf0e8000,0x3e793eacbf223f75,0xbedb3f5cbf7b3f6d,0x3f7dbf3e3ef13dc9,
0xbeb83f42bf753f7b,0x3f7ebf513f04bd49,0xbf7a3f77bf463ec4,0x3ee63cc9bedb3f4e,0xbf393ea13dc9bf0e,0xbefc3f58bf7d3f71,0x3e2fbf1d3f62bf80,0xbf7f3f6abf2c3e79,
0xbf6f3f27be95be48,0xbdfb3f13bf5c3f80,0xbe60be893f22bf6d,0xbf653f80bf673f18,0x3f31bf733f7fbf55,0xbf5f3f09be16beac,0x3f7cbf4a3ef18000,0xbd97becf3f3ebf78,
0xbe953f22bf6d3f80,0x3f7fbf623f0ebe48,0x3ef1bdc9bec43f35,0x3f46bf753f7bbf55,0x3f75bf463ec40000,0x3dc9bef13f55bf7b,0x3f62bf7f3f6dbf35,0xbf223e953e48bf0e,
0xbf753f46bec48000,0xbdc93ef1bf553f7b,0xbf623f7fbf6d3f35,0x3f22be95be483f0e,0xbe953f22bf6d3f80,0x3f7fbf623f0ebe48,0x3ef1bdc9bec43f35,0x3f46bf753f7bbf55,
0xbe2fbdfb3f22bf55,0xbf733f80bf5c3f2c,0x3ecfbf273f75bf80,0xbf773f58bedb3e16,0xbf7a3f5fbef13e48,0xbd973eb8bf4e3f71,0xbf313ee63dc9bec4,0xbf1d3f51bf803f78,
0x3f7cbf7e3f46bf0e,0xbea13cc93f04bf3e,0x3f6abf423e958000,0x3e89bf093f67bf7d,0x3e60befc3f62bf7b,0xbf7f3f6fbf183eac,0x3f39bf653f7fbf6d,0xbf4a3f13bd49be79,
0x3e79bd49bf0e3f35,0x3f71bf7d3f62bf46,0x3f18bedbbe483ec4,0x3f3ebf5c3f7fbf75,0xbf043f2cbf7b3f80,0x3f67bf4e3e95bdc9,0xbe163eacbf553f6d,0x3f80bf783f22bef1,
0xbf783f80bf553f35,0x3eacbe16bef13f22,0xbf4e3f67bf7b3f6d,0x3f2cbf04bdc93e95,0xbf5c3f3ebe488000,0xbedb3f18bf753f7f,0xbf7d3f71bf0e3ec4,0xbd493e79bf463f62,
0x3d97be2f3f46bf55,0xbf803f7ebf2c3f18,0x3e89beb83f62bf6d,0xbf7a3f73bf043edb,0x3ee6bf093f75bf7b,0xbf6a3f5fbeac3e79,0x3f1dbf313f7fbf80,0xbf513f42be163d49,
0x3f7fbf7c3f22bf0e,0x3cc9bdfb3f3ebf4e,0x3f77bf6f3ef1bec4,0x3e60bea13f5cbf67,0x3f65bf583e95be48,0x3ecfbefc3f71bf78,0x3f4abf393dc98000,0x3f13bf273f7dbf80,
0x3f35bf35bf803f80,0xbf353f3500000000,0x3f35bf35bf803f80,0xbf353f3500000000,0x3f35bf35bf803f80,0xbf353f3500000000,0x3f35bf35bf803f80,0xbf353f3500000000,
0x3f35bf3580008000,0x3f35bf35bf803f80,0x3f35bf3580008000,0x3f35bf35bf803f80,0x3f35bf3580008000,0x3f35bf35bf803f80,0x3f35bf3580008000,0x3f35bf35bf803f80,
0xbf65bf58bef1bf0e,0x3f6a3f5f3edb3f04,0xbf4abf39bf22bf35,0x3f513f423f183f2c,0xbf7fbf7cbdc9be48,0x3f803f7e3d493e16,0xbf77bf6fbe95bec4,0x3f7a3f733e793eac,
0xbee6bf093f623f55,0x3ecf3efcbf67bf5c,0xbf1dbf313f463f35,0x3f133f27bf4ebf3e,0xbd97be2f3f7f3f7b,0x3cc93dfbbf80bf7d,0xbe89beb83f753f6d,0x3e603ea1bf78bf71,
0x3f043f2cbf55bf35,0xbedbbf183f623f46,0x3e163eacbf7bbf6d,0xbd49be793f7f3f75,0x3f783f80be480000,0xbf71bf7d3e953dc9,0x3f4e3f67bf0ebec4,0xbf3ebf5c3f223ef1,
0xbf5cbf3ebf0ebf35,0x3f673f4e3ef13f22,0xbf7dbf71be48bec4,0x3f803f783dc93e95,0xbe79bd49bf7bbf80,0x3eac3e163f753f7f,0xbf18bedbbf55bf6d,0x3f2c3f043f463f62,
0x3f7a3f5f3e953f0e,0xbf7fbf6fbe16bedb,0x3f313ee63f463f6d,0xbf4abf13bf2cbf5c,0x3e2fbdfb3f7f3f7b,0xbea1bcc9bf78bf80,0xbecfbf273f623f35,0x3e893f09bf71bf4e,
0x3e603efcbf75bf55,0xbd97beb83f7d3f67,0x3f393f65bf22bec4,0xbf1dbf513f3e3f04,0x3f7c3f7ebdc93e48,0xbf73bf803e79bd49,0x3f6a3f423ef13f35,0xbf77bf58beacbf18,
0xbef1bdc9bf6dbf80,0x3f223e953f553f7b,0xbf75bf46bec4bf35,0x3f7f3f623e483f0e,0xbf62bf7f3ec40000,0x3f463f75bf0ebe48,0xbe95bf223f6d3f35,0x3dc93ef1bf7bbf55,
0xbf62bf7f3ec48000,0x3f463f75bf0ebe48,0xbe95bf223f6d3f35,0x3dc93ef1bf7bbf55,0x3ef13dc93f6d3f80,0xbf22be95bf55bf7b,0x3f753f463ec43f35,0xbf7fbf62be48bf0e,
0x3f313f73bf22be48,0xbefcbf583f4e3edb,0x3f7c3f4a3e953f35,0xbf7fbf6abd49bf04,0xbf6fbf27bef1bf55,0x3f7e3f513e793f2c,0xbe603e89bf7fbf6d,0x3ee6bcc93f713f7d,
0xbf39bea1bf46bf7b,0x3f5f3f093f183f67,0x3e2f3f1dbf75bf35,0x3d97becf3f803f5c,0xbeb8bf423f623f0e,0x3dfb3f13bf78bf3e,0xbf7abf773dc9bec4,0x3f653f80beac3e16,
0x3f803f4e3e483f35,0xbf78bf713dc9bef1,0x3edb3f5cbf55bec4,0xbe16bf2c3f753f22,0xbf3ebf7d3f0e0000,0x3f043f67bf46be95,0x3eacbe793f7b3f6d,0xbf18bd49bf62bf7f,
0x3d493f18bf7bbf35,0x3e79beac3f7f3f62,0xbf67bf04bf0ebf6d,0x3f7d3f3e3e953f46,0x3f2c3e163f553f80,0xbf5cbedbbf22bf75,0x3f713f78be483ec4,0xbf4ebf803ef1bdc9,
0x3f5f3eb83f223f7b,0xbf7cbf27beacbf5c,0xbea1bf583f623ec4,0xbcc93f1dbf7dbf2c,0xbf7ebf31be95bf55,0x3f7a3f65bd493f18,0xbd973f13bf7fbf35,0x3ecfbe893f783f67,
0x3efc3f6fbf46be48,0xbe2fbf423f713f04,0x3f733f093ef13f6d,0xbf80bf4abe16bf3e,0xbdfbbf393f753f0e,0xbe603ee6bf80bf4e,0xbf7fbf51bdc9bf35,0x3f6a3f77be793edb,
0x3f553e483f353f80,0xbf7bbf0ebec4bf6d,0x3f0e3f7bbf350000,0xbe48bf553f6d3ec4,0xbf55be48bf35bf80,0x3f7b3f0e3ec43f6d,0xbf0ebf7b3f350000,0x3e483f55bf6dbec4,
0x3f0e3f7bbf358000,0xbe48bf553f6d3ec4,0xbf55be48bf35bf80,0x3f7b3f0e3ec43f6d,0xbf0ebf7b3f358000,0x3e483f55bf6dbec4,0x3f553e483f353f80,0xbf7bbf0ebec4bf6d,
0x3efcbeb83f753f55,0xbf51bd97bf3ebf7d,0xbf73bf583dc9bf35,0x3f393f7ebf043eac,0xbf4abcc9bf46bf7b,0x3f7a3ee63edb3f78,0x3f423f7cbef13ec4,0xbecfbf773f4e3d49,
0x3f5f3f6fbe953f0e,0xbf13bf7f3f2cbe16,0x3ea1bf093f7f3f35,0xbf313dfbbf5cbf71,0xbf1dbf803f22be48,0x3e603f65bf67be79,0xbf273e2fbf62bf6d,0x3f6a3e893f183f80,
0x3edbbf043f7b3f35,0xbf4e3d49bf46bf75,0x3f2c3f7dbf0e3ec4,0xbe79bf713f623dc9,0x3eac3f78bf550000,0x3e16bf3e3f7f3ef1,0xbf80bf18be48bf6d,0x3f5c3f67be953f22,
0x3f673f5cbe483f35,0xbf18bf803f22be95,0xbf3e3e16bf55bf6d,0x3f783eac3ef13f7f,0xbf71be79bf0ebf80,0x3f7d3f2c3dc93f62,0x3d49bf4e3f7b3ec4,0xbf043edbbf75bf46,
0x3f31bea13f623f55,0xbf77be60bf04bf80,0xbf7cbf1dbdc9bf6d,0x3f423f6fbedb3f18,0x3ecf3f7fbf463e48,0x3dfbbf513f7d3eac,0x3f09befc3f753f35,0xbf65bcc9bf2cbf78,
0x3f393f73bef13f0e,0xbe89bf7a3f5cbd49,0x3e2fbf4a3f7f3ec4,0xbf273eb8bf67bf4e,0xbf6abd97bf22bf7b,0x3f7e3f133e163f71,0x3f583f5fbe953f35,0xbee6bf803f3ebe79,
0xbf7fbe95bec4bf80,0x3f623f46be483f55,0x3f22bef13f6d3f35,0xbf75bdc9bf0ebf7b,0x3dc93f75bf6d0000,0x3ef1bf223f7b3f0e,0xbf46bf623ec4bf35,0x3e953f7fbf553e48,
0xbdc9bf753f6d8000,0xbef13f22bf7bbf0e,0x3f463f62bec43f35,0xbe95bf7f3f55be48,0xbf7fbe95bec4bf80,0x3f623f46be483f55,0x3f22bef13f6d3f35,0xbf75bdc9bf0ebf7b,
0xbf7abefcbdc9bf7b,0x3f273f6abf043f2c,0x3f313f65bef13f35,0xbdfbbf7c3f67be16,0xbf133f1dbf75bf0e,0x3f73bcc93f183f71,0x3f6fbd973f223f6d,0xbf77bf09bd49bf78,
0x3e60bf5f3f7f3e48,0xbf423ecfbf5cbf3e,0xbf393ee6bf62bf35,0x3f7e3e2f3edb3f7d,0xbf51bf4a3e95bf55,0x3ea13f80bf4e3eac,0x3eb83f7fbf463ec4,0x3e89bf583f803e79,
0xbf18bf673f0ebf35,0xbd493f78bf753dc9,0x3f5c3f2cbe483f6d,0xbeacbf7d3f46bef1,0x3e16bf713f7b0000,0xbf3e3f04bf62bf22,0x3e793f80bf553ec4,0x3edbbf4e3f7f3e95,
0x3f4ebedb3f553f35,0xbf80be79be95bf7f,0xbf043f3ebf7bbec4,0x3f71be163f223f62,0x3f7d3eac3e483f80,0xbf2cbf5c3ef1bf46,0xbf783d49bf0ebf6d,0x3f673f18bdc93f75,
0x3ee6bf583f7f3e48,0xbf6f3e89bf2cbf4e,0xbf1d3f39bf75bec4,0x3f7cbd973f043f67,0x3f42bf133f623f0e,0xbf80bdfbbeacbf78,0xbf5f3ecfbf46bf35,0x3f7a3ea13e163f80,
0x3f653f09bdc93f7b,0xbeb8bf773f3ebf18,0xbf4abf313e95bf6d,0x3e2f3f7fbf5c3edb,0x3f273f51bef13f55,0x3cc9bf7e3f71be79,0xbefcbf6a3f22bf35,0xbe603f73bf7d3d49,
0x3f6d3ec400003f80,0xbec4bf6d3f35bf35,0xbf6dbec40000bf80,0x3ec43f6dbf353f35,0x3f6d3ec400003f80,0xbec4bf6d3f35bf35,0xbf6dbec40000bf80,0x3ec43f6dbf353f35,
0xbec43f6dbf808000,0x3f6dbec43f353f35,0x3ec4bf6d3f808000,0xbf6d3ec4bf35bf35,0xbec43f6dbf808000,0x3f6dbec43f353f35,0x3ec4bf6d3f808000,0xbf6d3ec4bf35bf35,
0x3d973f7cbf623f0e,0x3f31bf4a3f713e79,0xbe89bf6f3f46bf35,0xbf093f65bf7dbd49,0xbea13f7abf7f3e48,0x3f6abefc3f3e3f18,0x3dfbbf803f75bec4,0xbf513f27bf5cbedb,
0xbf7f3e2fbef1bf55,0x3f393f1dbeac3f78,0x3f77beb83f223f35,0xbf58bee63e16bf80,0xbf73be60bdc9bf7b,0x3ecf3f5fbf2c3f4e,0x3f7e3cc93e953f6d,0xbf13bf423f04bf67,
0xbf7d3eacbf0ebf35,0x3f3e3f04be953f7f,0x3f783d493e483f6d,0xbedbbf4e3f22bf62,0xbf183f67bf7b0000,0x3f80be793ef13f46,0x3f5cbf2c3f553ec4,0xbf71be16bdc9bf75,
0xbe16bf713f55bf35,0xbf2c3f5cbf75bdc9,0xbe793f80bf7b3ec4,0x3f67bf183f463ef1,0xbf4ebedb3e48bf80,0x3d493f78bf623f22,0x3f043f3ebf0e3f6d,0x3eacbf7d3f7fbe95,
0x3e2fbf7e3f75bf0e,0xbf653f31bf4ebeac,0x3ecf3f42bf223f6d,0x3efcbf7a3f80be79,0xbf58be893dc9bf7b,0x3d973f6fbf5c3f3e,0x3f80bea13ef13f35,0xbf1dbf133edbbf7d,
0x3f7cbdfb3e953f55,0xbee6bf393f18bf71,0xbf6a3f27bf46bec4,0x3f5f3e60bd493f78,0x3f09bf773f7fbe48,0xbf7f3eb8bf04bf2c,0x3cc93f73bf623f35,0x3f4abf513f673e16,
0xbf22bef13ec4bf80,0xbe953f7fbf7b3f0e,0xbdc93f75bf6d3f35,0x3f62bf463f553e48,0x3f46bf623f6d0000,0xbf753dc9be48bf55,0xbf7f3e95bec4bf35,0x3ef13f22bf0e3f7b,
0x3f46bf623f6d8000,0xbf753dc9be48bf55,0xbf7f3e95bec4bf35,0x3ef13f22bf0e3f7b,0x3f223ef1bec43f80,0x3e95bf7f3f7bbf0e,0x3dc9bf753f6dbf35,0xbf623f46bf55be48,
0x3f6fbf423f463e48,0xbf4abe2f3e16bf71,0xbe603f77bf753f35,0x3f73bf393f3e3e79,0xbcc93f65bf623f55,0x3f5fbf583f5c3d49,0xbf51bdfb3dc9bf6d,0xbd973f6abf673f4e,
0x3eb83f27bf223f7b,0x3f1dbf7c3f7dbeac,0xbf7a3e89be95bf35,0x3ea13f31bf2c3f78,0xbf803ee6bef1bf0e,0x3efc3f09bf043f80,0x3f13bf7e3f7fbec4,0xbf7f3ecfbedbbf18,
0xbeac3f78bf7b3f35,0x3f7dbf2c3f223e95,0x3f80bf183f0e3ec4,0xbf04bedb3ef1bf7f,0x3f67bf5c3f550000,0xbf4ebd493dc9bf62,0xbf3ebe163e48bf6d,0xbe793f71bf753f46,
0xbf713e79be48bf35,0x3e163f3ebf463f75,0x3d493f4ebf553f6d,0x3f5cbf673f62bdc9,0x3edb3f04bf0e3f80,0x3f18bf803f7fbef1,0x3f2cbf7d3f7bbec4,0xbf783eacbe95bf22,
0xbdfbbf313f46bf7b,0xbf583f73bf673e79,0x3f7fbf133ef13ec4,0xbeb8befc3f18bf80,0xbe893f6abf753f55,0x3f7cbf423f2c3e16,0xbf653e60bdc9bf35,0xbcc93f4abf5c3f71,
0x3f7ebf393f223e48,0xbf09bea13edbbf78,0xbd973f51bf623f6d,0x3f6fbf5f3f4ebd49,0xbf773ecfbe95bf0e,0x3e2f3f27bf3e3f7d,0x3ee6bf7a3f7fbf35,0xbf803f1dbf04beac,
0x3e483f0ebf353f80,0x3f55bf7b3f6dbec4,0x3f7bbf553f350000,0xbf0ebe483ec4bf6d,0xbe48bf0e3f35bf80,0xbf553f7bbf6d3ec4,0xbf7b3f55bf350000,0x3f0e3e48bec43f6d,
0xbf7b3f55bf358000,0x3f0e3e48bec43f6d,0x3e483f0ebf353f80,0x3f55bf7b3f6dbec4,0x3f7bbf553f358000,0xbf0ebe483ec4bf6d,0xbe48bf0e3f35bf80,0xbf553f7bbf6d3ec4,
0xbf1dbcc93e95bf55,0xbf093f73bf803f4e,0x3f27bf7c3f7fbf35,0xbf6f3efcbe79bedb,0x3e893ecfbf223f7b,0x3f51bf7f3f71bf04,0xbf653f7abf623ec4,0x3f39bdfbbe163f3e,
0x3f4abf803f75bf0e,0xbf583ea1bd49bf18,0x3f42be2fbdc93f35,0x3eb8bf5f3f78bf67,0xbf773f6abf463e48,0x3f133d97beac3f5c,0xbee6be603ef1bf6d,0xbf313f7ebf7d3f2c,
0x3f2cbe16be483f35,0x3f04bf673f7fbf62,0x3f71bf783f55bec4,0xbf183d493e95bf46,0xbf803f4ebf0e0000,0x3e793eacbf223f75,0xbedb3f5cbf7b3f6d,0x3f7dbf3e3ef13dc9,
0xbf3e3f7dbf7b3f35,0x3f5cbedb3dc93ef1,0x3eac3e79bf0e3f6d,0x3f4ebf803f75bf22,0x3d49bf183f55bf80,0xbf783f71bf463e95,0xbf673f04be48bec4,0xbe163f2cbf623f7f,
0xbecfbd973ef1bf55,0xbf4a3f7cbf783f3e,0x3f09bf5f3f7fbf6d,0xbf733f31beacbe16,0x3f80bf653f22be48,0xbe89be603f18bf67,0x3f13bdfbbe953f35,0x3f27bf6f3f80bf5c,
0x3f6abf7f3f62bf0e,0xbf1d3e2f3e79bf2c,0x3f58befc3dc93ec4,0x3ea1bf393f71bf7d,0x3cc93ee6bf463f7b,0x3f77bf7a3f4ebedb,0xbf513f7ebf753f35,0x3f42beb8bd493f04,
0x3e95bf223f6dbf80,0xbf7f3f62bf0e3e48,0xbef13dc93ec4bf35,0xbf463f75bf7b3f55,0xbf753f46bec40000,0xbdc93ef1bf553f7b,0xbf623f7fbf6d3f35,0x3f22be95be483f0e,
0x3f75bf463ec48000,0x3dc9bef13f55bf7b,0x3f62bf7f3f6dbf35,0xbf223e953e48bf0e,0x3e95bf223f6dbf80,0xbf7f3f62bf0e3e48,0xbef13dc93ec4bf35,0xbf463f75bf7b3f55,
0xbf133f4abf7f3f7b,0x3f65bf393e793d49,0xbf6f3f7fbf623f35,0x3efcbe60beac3f18,0x3f09be89be953f0e,0x3f42bf6a3f7dbf67,0xbcc93ea1bf463f6d,0x3f7ebf7c3f3ebf04,
0xbf513f1dbdc9be48,0xbee63f31bf783f80,0xbeb83d973ef1bf35,0xbf5f3f7abf713f4e,0xbf583f77bf753f55,0x3f27becfbe163edb,0xbf803f73bf223ec4,0x3dfb3e2fbf2c3f5c,
0x3f78bf803f55bf35,0xbeac3e163ef1bf22,0x3f4ebf673f7bbf6d,0xbf2c3f043dc9be95,0x3f5cbf3e3e480000,0x3edbbf183f75bf7f,0x3f7dbf713f0ebec4,0x3d49be793f46bf62,
0x3e79bd49bf0e3f35,0x3f71bf7d3f62bf46,0x3f18bedbbe483ec4,0x3f3ebf5c3f7fbf75,0xbf043f2cbf7b3f80,0x3f67bf4e3e95bdc9,0xbe163eacbf553f6d,0x3f80bf783f22bef1,
0xbf273f133dc9be48,0xbf393f4abf803f7d,0xbefc3ecf3e95bec4,0xbf583f65bf783f71,0xbea13e603ef1bf0e,0xbf6f3f77bf673f5c,0xbdfb3cc93f22bf35,0xbf7c3f7fbf4e3f3e,
0x3f42bf513f7fbf7b,0xbf313f1d3d49be16,0x3f5fbf6a3f75bf6d,0xbf093ee63e79beac,0x3f73bf7a3f62bf55,0xbeb83e893edbbf04,0x3f7ebf803f46bf35,0xbe2f3d973f18bf2c,
0x3f35bf35bf803f80,0xbf353f3500000000,0x3f35bf35bf803f80,0xbf353f3500000000,0x3f35bf35bf803f80,0xbf353f3500000000,0x3f35bf35bf803f80,0xbf353f3500000000,
0x3f35bf3580008000,0x3f35bf35bf803f80,0x3f35bf3580008000,0x3f35bf35bf803f80,0x3f35bf3580008000,0x3f35bf35bf803f80,0x3f35bf3580008000,0x3f35bf35bf803f80,
0xbf73bf7a3e953e48,0x3f6f3f77beacbe79,0xbf7ebf803dc90000,0x3f7c3f7fbe16bd49,0xbf42bf513f223f0e,0x3f393f4abf2cbf18,0xbf5fbf6a3ef13ec4,0x3f583f65bf04bedb,
0x3ea13e603f753f7b,0xbeb8be89bf71bf78,0x3dfb3cc93f7f3f80,0xbe2fbd97bf7dbf80,0x3f273f133f463f55,0xbf31bf1dbf3ebf4e,0x3efc3ecf3f623f6d,0xbf09bee6bf5cbf67,
0xbf5cbf3ebf0ebf35,0x3f673f4e3ef13f22,0xbf7dbf71be48bec4,0x3f803f783dc93e95,0xbe79bd49bf7bbf80,0x3eac3e163f753f7f,0xbf18bedbbf55bf6d,0x3f2c3f043f463f62,
0xbf04bf2c3f553f35,0x3edb3f18bf62bf46,0xbe16beac3f7b3f6d,0x3d493e79bf7fbf75,0xbf78bf803e488000,0x3f713f7dbe95bdc9,0xbf4ebf673f0e3ec4,0x3f3e3f5cbf22bef1,
0xbf09be89bf62bf7b,0x3f273ecf3f4e3f71,0x3cc93ea1bf7fbf6d,0x3dfbbe2f3f803f78,0x3f133f4abf46bf0e,0xbee6bf313f5c3f2c,0x3f6f3f7fbe950000,0xbf5fbf7a3edb3e16,
0xbf58bf773ef13e48,0x3f423f6abf18beac,0xbf80bf73bdc9bec4,0x3f7e3f7cbd493e79,0xbf51bf1dbf22bf55,0x3f653f393f043f3e,0xbeb8bd97bf75bf80,0x3efc3e603f673f7d,
0x3ef13dc93f6d3f80,0xbf22be95bf55bf7b,0x3f753f463ec43f35,0xbf7fbf62be48bf0e,0x3f623f7fbec40000,0xbf46bf753f0e3e48,0x3e953f22bf6dbf35,0xbdc9bef13f7b3f55,
0x3f623f7fbec48000,0xbf46bf753f0e3e48,0x3e953f22bf6dbf35,0xbdc9bef13f7b3f55,0xbef1bdc9bf6dbf80,0x3f223e953f553f7b,0xbf75bf46bec4bf35,0x3f7f3f623e483f0e,
0x3cc9bee63f7f3f55,0xbe893e60bf7dbf71,0xbf51bf7e3ef10000,0x3f273f6fbf2cbe79,0x3f6a3f7fbe953e48,0xbf4abf7c3f043d49,0x3f583efc3f223f6d,0xbf73bf31bedbbf4e,
0x3f803f653dc93f0e,0xbf77bf7a3e16beac,0x3f133dfb3f623f80,0xbf42beb8bf3ebf78,0xbecf3d97bf75bf7b,0x3f1d3e2f3f5c3f80,0x3f093f5fbf46bec4,0xbea1bf393f673f18,
0xbd49bf183f7b3f35,0xbe793eacbf7fbf62,0x3f673f043f0e3f6d,0xbf7dbf3ebe95bf46,0xbf2cbe16bf55bf80,0x3f5c3edb3f223f75,0xbf71bf783e48bec4,0x3f4e3f80bef13dc9,
0x3f803f4e3e483f35,0xbf78bf713dc9bef1,0x3edb3f5cbf55bec4,0xbe16bf2c3f753f22,0xbf3ebf7d3f0e8000,0x3f043f67bf46be95,0x3eacbe793f7b3f6d,0xbf18bd49bf62bf7f,
0x3e89becf3f7f3f55,0xbf133d97bf67bf78,0xbf65bf7a3e95bec4,0x3f313f7ebf183d49,0xbf1d3cc9bf62bf7b,0x3f583ea13f2c3f7d,0x3f273f7cbf220000,0xbeb8bf5f3f5c3eac,
0x3f773f6abdc93f0e,0xbf51bf7f3edbbe79,0x3ee6be603f753f6d,0xbf39bdfbbf4ebf80,0xbf4abf803ef1be48,0x3f093f73bf3ebe16,0xbf42be2fbf46bf80,0x3f6f3efc3f043f71,
0x3f553e483f353f80,0xbf7bbf0ebec4bf6d,0x3f0e3f7bbf350000,0xbe48bf553f6d3ec4,0xbf55be48bf35bf80,0x3f7b3f0e3ec43f6d,0xbf0ebf7b3f350000,0x3e483f55bf6dbec4,
0x3f0e3f7bbf358000,0xbe48bf553f6d3ec4,0xbf55be48bf35bf80,0x3f7b3f0e3ec43f6d,0xbf0ebf7b3f358000,0x3e483f55bf6dbec4,0x3f553e483f353f80,0xbf7bbf0ebec4bf6d,
0x3f773ecf3ef13f7b,0xbf7cbf42bd49bf4e,0xbee6bf7a3f460000,0x3cc93f4abf78bedb,0xbf7ebf39bdc9bf55,0x3f583f73beac3f04,0x3d973f51bf75bec4,0x3eb8befc3f7d3f3e,
0x3e893f6abf62be48,0x3e2fbf273f803f18,0x3f653e603f223f80,0xbf80bf1dbe79bf67,0x3dfbbf313f7f3f0e,0xbf093ea1bf71bf5c,0xbf7fbf13be95bf6d,0x3f6f3f5fbe163f2c,
0x3f673f5cbe483f35,0xbf18bf803f22be95,0xbf3e3e16bf55bf6d,0x3f783eac3ef13f7f,0xbf71be79bf0ebf80,0x3f7d3f2c3dc93f62,0x3d49bf4e3f7b3ec4,0xbf043edbbf75bf46,
0xbedb3f04bf7bbf35,0x3f4ebd493f463f75,0xbf2cbf7d3f0ebec4,0x3e793f71bf62bdc9,0xbeacbf783f558000,0xbe163f3ebf7fbef1,0x3f803f183e483f6d,0xbf5cbf673e95bf22,
0x3cc93f65bf75be48,0x3efcbf093f783f2c,0x3f51bdfb3f463f6d,0xbf7fbecfbeacbf7d,0xbf6fbf423dc9bf55,0x3f1d3f7cbf183edb,0x3e603f77bf620000,0x3ea1bf313f803f04,
0xbf80bee6be95bf7b,0x3f5f3f58be793f3e,0x3f133f7ebf223ec4,0xbd97bf6a3f713e16,0x3eb8bf273f7f3f0e,0xbf4a3e2fbf4ebf67,0xbf7abe89bef1bf80,0x3f733f39bd493f5c,
0x3f7f3e953ec43f80,0xbf62bf463e48bf55,0xbf223ef1bf6dbf35,0x3f753dc93f0e3f7b,0xbdc9bf753f6d0000,0xbef13f22bf7bbf0e,0x3f463f62bec43f35,0xbe95bf7f3f55be48,
0x3dc93f75bf6d8000,0x3ef1bf223f7b3f0e,0xbf46bf623ec4bf35,0x3e953f7fbf553e48,0x3f7f3e953ec43f80,0xbf62bf463e48bf55,0xbf223ef1bf6dbf35,0x3f753dc93f0e3f7b,
0x3f093f77bf223f0e,0x3d97bf6f3f783d49,0x3cc9bf733f750000,0xbf1d3f13bf71bf18,0x3f7c3dfb3ef13f7b,0xbf65bf313e16bf67,0xbf6abf273dc9bf6d,0x3efc3f7abf2c3f04,
0xbf583e89bf46bf55,0x3f7f3eb83e793f80,0x3f803ea13e953f80,0xbf4abf513eacbf4e,0x3e2f3f7ebf623e48,0x3ee6bf393f7d3edb,0x3ecfbf423f7f3ec4,0xbf5f3e60bf3ebf5c,
0xbf4e3edbbf55bf35,0x3f803e793e953f7f,0x3f04bf3e3f7b3ec4,0xbf713e16bf22bf62,0xbf7dbeacbe48bf80,0x3f2c3f5cbef13f46,0x3f78bd493f0e3f6d,0xbf67bf183dc9bf75,
0xbf18bf673f0ebf35,0xbd493f78bf753dc9,0x3f5c3f2cbe483f6d,0xbeacbf7d3f46bef1,0x3e16bf713f7b8000,0xbf3e3f04bf62bf22,0x3e793f80bf553ec4,0x3edbbf4e3f7f3e95,
0xbea1bf7a3f46bf0e,0xbecf3f5fbf80be16,0x3dfb3f80bf623ec4,0x3f13bf423f783eac,0x3d97bf7c3f75be48,0xbf393f1dbf67bf04,0xbe893f6fbf7f0000,0x3f58bee63f4e3f2c,
0x3f73be603f223f55,0xbf6abefc3d49bf7d,0xbf7e3cc9bef1bf6d,0x3f513f27be793f71,0x3f7f3e2f3e953f7b,0xbf31bf4a3edbbf5c,0xbf77beb8bdc9bf80,0x3f093f65bf183f3e,
0x3f6d3ec400003f80,0xbec4bf6d3f35bf35,0xbf6dbec40000bf80,0x3ec43f6dbf353f35,0x3f6d3ec400003f80,0xbec4bf6d3f35bf35,0xbf6dbec40000bf80,0x3ec43f6dbf353f35,
0xbec43f6dbf808000,0x3f6dbec43f353f35,0x3ec4bf6d3f808000,0xbf6d3ec4bf35bf35,0xbec43f6dbf808000,0x3f6dbec43f353f35,0x3ec4bf6d3f808000,0xbf6d3ec4bf35bf35,
0xbf273f51bf75be48,0x3f80bdfb3edb3f5c,0x3efcbf6a3f7f0000,0xbf7a3ea1bf18bf3e,0xbf653f09bf46bf0e,0x3f6f3e893d493f7d,0x3f4abf313f623ec4,0xbf7cbd97be79bf71,
0xbf42bf133e95bf7b,0x3cc93f7ebf673f04,0x3f5f3ecfbdc93f80,0xbe60bf733f4ebf2c,0xbee6bf583f22bf55,0xbeb83f77bf803e16,0x3f1d3f39bef13f6d,0x3e2fbf7f3f78beac,
0xbe16bf713f55bf35,0xbf2c3f5cbf75bdc9,0xbe793f80bf7b3ec4,0x3f67bf183f463ef1,0xbf4ebedb3e48bf80,0x3d493f78bf623f22,0x3f043f3ebf0e3f6d,0x3eacbf7d3f7fbe95,
0x3f7dbeac3f0e3f35,0xbf3ebf043e95bf7f,0xbf78bd49be48bf6d,0x3edb3f4ebf223f62,0x3f18bf673f7b8000,0xbf803e79bef1bf46,0xbf5c3f2cbf55bec4,0x3f713e163dc93f75,
0x3f133f1dbef13f7b,0x3ea1bf803f7dbedb,0xbf6fbd97bdc9bf6d,0x3e893f58bf3e3f5c,0x3f7abefc3f223f0e,0xbf42becf3e79bf80,0xbf313f65bf750000,0x3f7ebe2f3eac3f4e,
0xbf513f4abf62be48,0x3f733cc93e163f67,0x3eb8bf7f3f7fbec4,0xbf773f09bf2cbf04,0x3e603f5fbf463f55,0x3f27bf6a3f78bd49,0xbf39bee63e95bf80,0xbdfb3f7cbf713f18,
0x3f223ef1bec43f80,0x3e95bf7f3f7bbf0e,0x3dc9bf753f6dbf35,0xbf623f46bf55be48,0xbf463f62bf6d0000,0x3f75bdc93e483f55,0x3f7fbe953ec43f35,0xbef1bf223f0ebf7b,
0xbf463f62bf6d8000,0x3f75bdc93e483f55,0x3f7fbe953ec43f35,0xbef1bf223f0ebf7b,0xbf22bef13ec4bf80,0xbe953f7fbf7b3f0e,0xbdc93f75bf6d3f35,0x3f62bf463f553e48,
0xbf6a3d97bdc9bf55,0x3dfb3f51bf4e3f67,0x3f58bf5f3f620000,0xbf653cc9bd49bf5c,0x3f39bf733f75be48,0xbf773e60be79bf3e,0x3e2f3f4abf463f6d,0x3f42bf6f3f71be16,
0x3ecfbf7f3f7fbf0e,0xbf7e3f13bf18bedb,0x3f093efcbef13f80,0x3ee6bf803f80bf04,0x3f313ea1be953f7b,0x3e89bf7a3f78bf2c,0xbf7c3f1dbf22bec4,0x3f273eb8beac3f7d,
0x3f71be793e483f35,0xbe16bf3e3f46bf75,0xbd49bf4e3f55bf6d,0xbf5c3f67bf623dc9,0xbedbbf043f0ebf80,0xbf183f80bf7f3ef1,0xbf2c3f7dbf7b3ec4,0x3f78beac3e953f22,
0xbeac3f78bf7b3f35,0x3f7dbf2c3f223e95,0x3f80bf183f0e3ec4,0xbf04bedb3ef1bf7f,0x3f67bf5c3f558000,0xbf4ebd493dc9bf62,0xbf3ebe163e48bf6d,0xbe793f71bf753f46,
0xbf4a3cc93dc9bf55,0xbe603f65bf713f5c,0x3f42bf7c3f75bec4,0xbf6a3e89be16bf2c,0x3efc3eb8bef13f7b,0x3f13bf7f3f80bf18,0xbf733f58bf460000,0x3f313dfbbe793f67,
0x3f1dbf803f7fbf0e,0xbf7a3ee6beacbf04,0x3f273e2fbe953f6d,0x3ecfbf773f7dbf3e,0xbf5f3f6fbf623e48,0x3f51bd97bd493f4e,0xbea1bf093f22bf80,0xbf393f7ebf783edb,
0x3e483f0ebf353f80,0x3f55bf7b3f6dbec4,0x3f7bbf553f350000,0xbf0ebe483ec4bf6d,0xbe48bf0e3f35bf80,0xbf553f7bbf6d3ec4,0xbf7b3f55bf350000,0x3f0e3e48bec43f6d,
0xbf7b3f55bf358000,0x3f0e3e48bec43f6d,0x3e483f0ebf353f80,0x3f55bf7b3f6dbec4,0x3f7bbf553f358000,0xbf0ebe483ec4bf6d,0xbe48bf0e3f35bf80,0xbf553f7bbf6d3ec4,
0x3dfbbf393f62bf7b,0xbf7a3f65bf3e3e16,0x3f7fbf513f220000,0xbecfbe893f04bf71,0xbefc3f6fbf7f3f55,0x3f7cbf273edb3e79,0xbf733f09be95bec4,0x3cc93f1dbf4e3f80,
0x3f7ebf313ef13e48,0xbe60bee63f2cbf7d,0x3d973f13bf463f80,0x3f6abf773f5cbeac,0xbf5f3eb8bdc9bf0e,0xbe2f3f42bf673f78,0x3ea1bf583f75bf6d,0xbf803f4abf18bd49,
0xbf3e3f7dbf7b3f35,0x3f5cbedb3dc93ef1,0x3eac3e79bf0e3f6d,0x3f4ebf803f75bf22,0x3d49bf183f55bf80,0xbf783f71bf463e95,0xbf673f04be48bec4,0xbe163f2cbf623f7f,
0xbf2c3e163e48bf35,0xbf043f67bf7f3f62,0xbf713f78bf553ec4,0x3f18bd49be953f46,0x3f80bf4e3f0e8000,0xbe79beac3f22bf75,0x3edbbf5c3f7bbf6d,0xbf7d3f3ebef1bdc9,
0x3f6fbf273e953e48,0x3dfbbf133f5cbf80,0x3e603e89bf223f6d,0x3f65bf803f67bf18,0xbf313f73bf7f3f55,0x3f5fbf093e163eac,0xbf7c3f4abef10000,0x3d973ecfbf3e3f78,
0xbeb83f42bf753f7b,0x3f7ebf513f04bd49,0xbf7a3f77bf463ec4,0x3ee63cc9bedb3f4e,0xbf393ea13dc9bf0e,0xbefc3f58bf7d3f71,0x3e2fbf1d3f62bf80,0xbf7f3f6abf2c3e79,
0xbe953f22bf6d3f80,0x3f7fbf623f0ebe48,0x3ef1bdc9bec43f35,0x3f46bf753f7bbf55,0x3f75bf463ec40000,0x3dc9bef13f55bf7b,0x3f62bf7f3f6dbf35,0xbf223e953e48bf0e,
0xbf753f46bec48000,0xbdc93ef1bf553f7b,0xbf623f7fbf6d3f35,0x3f22be95be483f0e,0xbe953f22bf6d3f80,0x3f7fbf623f0ebe48,0x3ef1bdc9bec43f35,0x3f46bf753f7bbf55,
0x3f7cbf7e3f46bf0e,0xbea13cc93f04bf3e,0x3f6abf423e950000,0x3e89bf093f67bf7d,0x3e60befc3f62bf7b,0xbf7f3f6fbf183eac,0x3f39bf653f7fbf6d,0xbf4a3f13bd49be79,
0x3e2f3dfbbf223f55,0x3f73bf803f5cbf2c,0xbecf3f27bf753f80,0x3f77bf583edbbe16,0x3f7abf5f3ef1be48,0x3d97beb83f4ebf71,0x3f31bee6bdc93ec4,0x3f1dbf513f80bf78,
0xbe793d493f0ebf35,0xbf713f7dbf623f46,0xbf183edb3e48bec4,0xbf3e3f5cbf7f3f75,0x3f04bf2c3f7bbf80,0xbf673f4ebe953dc9,0x3e16beac3f55bf6d,0xbf803f78bf223ef1,
0x3f78bf803f55bf35,0xbeac3e163ef1bf22,0x3f4ebf673f7bbf6d,0xbf2c3f043dc9be95,0x3f5cbf3e3e488000,0x3edbbf183f75bf7f,0x3f7dbf713f0ebec4,0x3d49be793f46bf62,
0xbf7f3f7cbf223f0e,0xbcc93dfbbf3e3f4e,0xbf773f6fbef13ec4,0xbe603ea1bf5c3f67,0xbf653f58be953e48,0xbecf3efcbf713f78,0xbf4a3f39bdc90000,0xbf133f27bf7d3f80,
0x3d97be2f3f46bf55,0xbf803f7ebf2c3f18,0x3e89beb83f62bf6d,0xbf7a3f73bf043edb,0x3ee6bf093f75bf7b,0xbf6a3f5fbeac3e79,0x3f1dbf313f7fbf80,0xbf513f42be163d49,
0x3f35bf35bf803f80,0xbf353f3500000000,0x3f35bf35bf803f80,0xbf353f3500000000,0x3f35bf35bf803f80,0xbf353f3500000000,0x3f35bf35bf803f80,0xbf353f3500000000,
0x3f35bf3580008000,0x3f35bf35bf803f80,0x3f35bf3580008000,0x3f35bf35bf803f80,0x3f35bf3580008000,0x3f35bf35bf803f80,0x3f35bf3580008000,0x3f35bf35bf803f80,
0xbee6bf093f623f55,0x3ecf3efcbf67bf5c,0xbf1dbf313f463f35,0x3f133f27bf4ebf3e,0xbd97be2f3f7f3f7b,0x3cc93dfbbf80bf7d,0xbe89beb83f753f6d,0x3e603ea1bf78bf71,
0x3f653f583ef13f0e,0xbf6abf5fbedbbf04,0x3f4a3f393f223f35,0xbf51bf42bf18bf2c,0x3f7f3f7c3dc93e48,0xbf80bf7ebd49be16,0x3f773f6f3e953ec4,0xbf7abf73be79beac,
0xbf04bf2c3f553f35,0x3edb3f18bf62bf46,0xbe16beac3f7b3f6d,0x3d493e79bf7fbf75,0xbf78bf803e480000,0x3f713f7dbe95bdc9,0xbf4ebf673f0e3ec4,0x3f3e3f5cbf22bef1,
0x3f5c3f3e3f0e3f35,0xbf67bf4ebef1bf22,0x3f7d3f713e483ec4,0xbf80bf78bdc9be95,0x3e793d493f7b3f80,0xbeacbe16bf75bf7f,0x3f183edb3f553f6d,0xbf2cbf04bf46bf62,
0xbe60befc3f753f55,0x3d973eb8bf7dbf67,0xbf39bf653f223ec4,0x3f1d3f51bf3ebf04,0xbf7cbf7e3dc9be48,0x3f733f80be793d49,0xbf6abf42bef1bf35,0x3f773f583eac3f18,
0x3f7a3f5f3e953f0e,0xbf7fbf6fbe16bedb,0x3f313ee63f463f6d,0xbf4abf13bf2cbf5c,0x3e2fbdfb3f7f3f7b,0xbea1bcc9bf78bf80,0xbecfbf273f623f35,0x3e893f09bf71bf4e,
0xbef1bdc9bf6dbf80,0x3f223e953f553f7b,0xbf75bf46bec4bf35,0x3f7f3f623e483f0e,0xbf62bf7f3ec40000,0x3f463f75bf0ebe48,0xbe95bf223f6d3f35,0x3dc93ef1bf7bbf55,
0xbf62bf7f3ec48000,0x3f463f75bf0ebe48,0xbe95bf223f6d3f35,0x3dc93ef1bf7bbf55,0x3ef13dc93f6d3f80,0xbf22be95bf55bf7b,0x3f753f463ec43f35,0xbf7fbf62be48bf0e,
0xbf39bea1bf46bf7b,0x3f5f3f093f183f67,0x3e2f3f1dbf75bf35,0x3d97becf3f803f5c,0xbeb8bf423f623f0e,0x3dfb3f13bf78bf3e,0xbf7abf773dc9bec4,0x3f653f80beac3e16,
0xbf31bf733f223e48,0x3efc3f58bf4ebedb,0xbf7cbf4abe95bf35,0x3f7f3f6a3d493f04,0x3f6f3f273ef13f55,0xbf7ebf51be79bf2c,0x3e60be893f7f3f6d,0xbee63cc9bf71bf7d,
0xbf80bf4ebe48bf35,0x3f783f71bdc93ef1,0xbedbbf5c3f553ec4,0x3e163f2cbf75bf22,0x3f3e3f7dbf0e0000,0xbf04bf673f463e95,0xbeac3e79bf7bbf6d,0x3f183d493f623f7f,
0xbd49bf183f7b3f35,0xbe793eacbf7fbf62,0x3f673f043f0e3f6d,0xbf7dbf3ebe95bf46,0xbf2cbe16bf55bf80,0x3f5c3edb3f223f75,0xbf71bf783e48bec4,0x3f4e3f80bef13dc9,
0xbefcbf6f3f463e48,0x3e2f3f42bf71bf04,0xbf73bf09bef1bf6d,0x3f803f4a3e163f3e,0x3dfb3f39bf75bf0e,0x3e60bee63f803f4e,0x3f7f3f513dc93f35,0xbf6abf773e79bedb,
0x3f5f3eb83f223f7b,0xbf7cbf27beacbf5c,0xbea1bf583f623ec4,0xbcc93f1dbf7dbf2c,0xbf7ebf31be95bf55,0x3f7a3f65bd493f18,0xbd973f13bf7fbf35,0x3ecfbe893f783f67,
0x3f553e483f353f80,0xbf7bbf0ebec4bf6d,0x3f0e3f7bbf350000,0xbe48bf553f6d3ec4,0xbf55be48bf35bf80,0x3f7b3f0e3ec43f6d,0xbf0ebf7b3f350000,0x3e483f55bf6dbec4,
0x3f0e3f7bbf358000,0xbe48bf553f6d3ec4,0xbf55be48bf35bf80,0x3f7b3f0e3ec43f6d,0xbf0ebf7b3f358000,0x3e483f55bf6dbec4,0x3f553e483f353f80,0xbf7bbf0ebec4bf6d,
0x3f5f3f6fbe953f0e,0xbf13bf7f3f2cbe16,0x3ea1bf093f7f3f35,0xbf313dfbbf5cbf71,0xbf1dbf803f22be48,0x3e603f65bf67be79,0xbf273e2fbf62bf6d,0x3f6a3e893f183f80,
0xbefc3eb8bf75bf55,0x3f513d973f3e3f7d,0x3f733f58bdc93f35,0xbf39bf7e3f04beac,0x3f4a3cc93f463f7b,0xbf7abee6bedbbf78,0xbf42bf7c3ef1bec4,0x3ecf3f77bf4ebd49,
0xbedb3f04bf7bbf35,0x3f4ebd493f463f75,0xbf2cbf7d3f0ebec4,0x3e793f71bf62bdc9,0xbeacbf783f550000,0xbe163f3ebf7fbef1,0x3f803f183e483f6d,0xbf5cbf673e95bf22,
0xbf67bf5c3e48bf35,0x3f183f80bf223e95,0x3f3ebe163f553f6d,0xbf78beacbef1bf7f,0x3f713e793f0e3f80,0xbf7dbf2cbdc9bf62,0xbd493f4ebf7bbec4,0x3f04bedb3f753f46,
0xbf39bf733ef1bf0e,0x3e893f7abf5c3d49,0xbe2f3f4abf7fbec4,0x3f27beb83f673f4e,0x3f6a3d973f223f7b,0xbf7ebf13be16bf71,0xbf58bf5f3e95bf35,0x3ee63f80bf3e3e79,
0x3f31bea13f623f55,0xbf77be60bf04bf80,0xbf7cbf1dbdc9bf6d,0x3f423f6fbedb3f18,0x3ecf3f7fbf463e48,0x3dfbbf513f7d3eac,0x3f09befc3f753f35,0xbf65bcc9bf2cbf78,
0xbf7fbe95bec4bf80,0x3f623f46be483f55,0x3f22bef13f6d3f35,0xbf75bdc9bf0ebf7b,0x3dc93f75bf6d0000,0x3ef1bf223f7b3f0e,0xbf46bf623ec4bf35,0x3e953f7fbf553e48,
0xbdc9bf753f6d8000,0xbef13f22bf7bbf0e,0x3f463f62bec43f35,0xbe95bf7f3f55be48,0xbf7fbe95bec4bf80,0x3f623f46be483f55,0x3f22bef13f6d3f35,0xbf75bdc9bf0ebf7b,
0x3e60bf5f3f7f3e48,0xbf423ecfbf5cbf3e,0xbf393ee6bf62bf35,0x3f7e3e2f3edb3f7d,0xbf51bf4a3e95bf55,0x3ea13f80bf4e3eac,0x3eb83f7fbf463ec4,0x3e89bf583f803e79,
0x3f7a3efc3dc93f7b,0xbf27bf6a3f04bf2c,0xbf31bf653ef1bf35,0x3dfb3f7cbf673e16,0x3f13bf1d3f753f0e,0xbf733cc9bf18bf71,0xbf6f3d97bf22bf6d,0x3f773f093d493f78,
0x3f183f67bf0e3f35,0x3d49bf783f75bdc9,0xbf5cbf2c3e48bf6d,0x3eac3f7dbf463ef1,0xbe163f71bf7b0000,0x3f3ebf043f623f22,0xbe79bf803f55bec4,0xbedb3f4ebf7fbe95,
0xbf4e3edbbf55bf35,0x3f803e793e953f7f,0x3f04bf3e3f7b3ec4,0xbf713e16bf22bf62,0xbf7dbeacbe48bf80,0x3f2c3f5cbef13f46,0x3f78bd493f0e3f6d,0xbf67bf183dc9bf75,
0xbf65bf093dc9bf7b,0x3eb83f77bf3e3f18,0x3f4a3f31be953f6d,0xbe2fbf7f3f5cbedb,0xbf27bf513ef1bf55,0xbcc93f7ebf713e79,0x3efc3f6abf223f35,0x3e60bf733f7dbd49,
0x3ee6bf583f7f3e48,0xbf6f3e89bf2cbf4e,0xbf1d3f39bf75bec4,0x3f7cbd973f043f67,0x3f42bf133f623f0e,0xbf80bdfbbeacbf78,0xbf5f3ecfbf46bf35,0x3f7a3ea13e163f80,
0x3f6d3ec400003f80,0xbec4bf6d3f35bf35,0xbf6dbec40000bf80,0x3ec43f6dbf353f35,0x3f6d3ec400003f80,0xbec4bf6d3f35bf35,0xbf6dbec40000bf80,0x3ec43f6dbf353f35,
0xbec43f6dbf808000,0x3f6dbec43f353f35,0x3ec4bf6d3f808000,0xbf6d3ec4bf35bf35,0xbec43f6dbf808000,0x3f6dbec43f353f35,0x3ec4bf6d3f808000,0xbf6d3ec4bf35bf35,
0xbf7f3e2fbef1bf55,0x3f393f1dbeac3f78,0x3f77beb83f223f35,0xbf58bee63e16bf80,0xbf73be60bdc9bf7b,0x3ecf3f5fbf2c3f4e,0x3f7e3cc93e953f6d,0xbf13bf423f04bf67,
0xbd97bf7c3f62bf0e,0xbf313f4abf71be79,0x3e893f6fbf463f35,0x3f09bf653f7d3d49,0x3ea1bf7a3f7fbe48,0xbf6a3efcbf3ebf18,0xbdfb3f80bf753ec4,0x3f51bf273f5c3edb,
0x3f7dbeac3f0e3f35,0xbf3ebf043e95bf7f,0xbf78bd49be48bf6d,0x3edb3f4ebf223f62,0x3f18bf673f7b0000,0xbf803e79bef1bf46,0xbf5c3f2cbf55bec4,0x3f713e163dc93f75,
0x3e163f71bf553f35,0x3f2cbf5c3f753dc9,0x3e79bf803f7bbec4,0xbf673f18bf46bef1,0x3f4e3edbbe483f80,0xbd49bf783f62bf22,0xbf04bf3e3f0ebf6d,0xbeac3f7dbf7f3e95,
0xbf7c3dfbbe95bf55,0x3ee63f39bf183f71,0x3f6abf273f463ec4,0xbf5fbe603d49bf78,0xbf093f77bf7f3e48,0x3f7fbeb83f043f2c,0xbcc9bf733f62bf35,0xbf4a3f51bf67be16,
0x3e2fbf7e3f75bf0e,0xbf653f31bf4ebeac,0x3ecf3f42bf223f6d,0x3efcbf7a3f80be79,0xbf58be893dc9bf7b,0x3d973f6fbf5c3f3e,0x3f80bea13ef13f35,0xbf1dbf133edbbf7d,
0xbf22bef13ec4bf80,0xbe953f7fbf7b3f0e,0xbdc93f75bf6d3f35,0x3f62bf463f553e48,0x3f46bf623f6d0000,0xbf753dc9be48bf55,0xbf7f3e95bec4bf35,0x3ef13f22bf0e3f7b,
0x3f46bf623f6d8000,0xbf753dc9be48bf55,0xbf7f3e95bec4bf35,0x3ef13f22bf0e3f7b,0x3f223ef1bec43f80,0x3e95bf7f3f7bbf0e,0x3dc9bf753f6dbf35,0xbf623f46bf55be48,
0x3eb83f27bf223f7b,0x3f1dbf7c3f7dbeac,0xbf7a3e89be95bf35,0x3ea13f31bf2c3f78,0xbf803ee6bef1bf0e,0x3efc3f09bf043f80,0x3f13bf7e3f7fbec4,0xbf7f3ecfbedbbf18,
0xbf6f3f42bf46be48,0x3f4a3e2fbe163f71,0x3e60bf773f75bf35,0xbf733f39bf3ebe79,0x3cc9bf653f62bf55,0xbf5f3f58bf5cbd49,0x3f513dfbbdc93f6d,0x3d97bf6a3f67bf4e,
0x3eacbf783f7bbf35,0xbf7d3f2cbf22be95,0xbf803f18bf0ebec4,0x3f043edbbef13f7f,0xbf673f5cbf550000,0x3f4e3d49bdc93f62,0x3f3e3e16be483f6d,0x3e79bf713f75bf46,
0x3f71be793e483f35,0xbe16bf3e3f46bf75,0xbd49bf4e3f55bf6d,0xbf5c3f67bf623dc9,0xbedbbf043f0ebf80,0xbf183f80bf7f3ef1,0xbf2c3f7dbf7b3ec4,0x3f78beac3e953f22,
0xbf7e3f39bf22be48,0x3f093ea1bedb3f78,0x3d97bf513f62bf6d,0xbf6f3f5fbf4e3d49,0x3f77becf3e953f0e,0xbe2fbf273f3ebf7d,0xbee63f7abf7f3f35,0x3f80bf1d3f043eac,
0xbdfbbf313f46bf7b,0xbf583f73bf673e79,0x3f7fbf133ef13ec4,0xbeb8befc3f18bf80,0xbe893f6abf753f55,0x3f7cbf423f2c3e16,0xbf653e60bdc9bf35,0xbcc93f4abf5c3f71,
0x3e483f0ebf353f80,0x3f55bf7b3f6dbec4,0x3f7bbf553f350000,0xbf0ebe483ec4bf6d,0xbe48bf0e3f35bf80,0xbf553f7bbf6d3ec4,0xbf7b3f55bf350000,0x3f0e3e48bec43f6d,
0xbf7b3f55bf358000,0x3f0e3e48bec43f6d,0x3e483f0ebf353f80,0x3f55bf7b3f6dbec4,0x3f7bbf553f358000,0xbf0ebe483ec4bf6d,0xbe48bf0e3f35bf80,0xbf553f7bbf6d3ec4,
0x3f4abf803f75bf0e,0xbf583ea1bd49bf18,0x3f42be2fbdc93f35,0x3eb8bf5f3f78bf67,0xbf773f6abf463e48,0x3f133d97beac3f5c,0xbee6be603ef1bf6d,0xbf313f7ebf7d3f2c,
0x3f1d3cc9be953f55,0x3f09bf733f80bf4e,0xbf273f7cbf7f3f35,0x3f6fbefc3e793edb,0xbe89becf3f22bf7b,0xbf513f7fbf713f04,0x3f65bf7a3f62bec4,0xbf393dfb3e16bf3e,
0xbf2c3e163e48bf35,0xbf043f67bf7f3f62,0xbf713f78bf553ec4,0x3f18bd49be953f46,0x3f80bf4e3f0e0000,0xbe79beac3f22bf75,0x3edbbf5c3f7bbf6d,0xbf7d3f3ebef1bdc9,
0x3f3ebf7d3f7bbf35,0xbf5c3edbbdc9bef1,0xbeacbe793f0ebf6d,0xbf4e3f80bf753f22,0xbd493f18bf553f80,0x3f78bf713f46be95,0x3f67bf043e483ec4,0x3e16bf2c3f62bf7f,
0xbf6a3f7fbf623f0e,0x3f1dbe2fbe793f2c,0xbf583efcbdc9bec4,0xbea13f39bf713f7d,0xbcc9bee63f46bf7b,0xbf773f7abf4e3edb,0x3f51bf7e3f75bf35,0xbf423eb83d49bf04,
0xbecfbd973ef1bf55,0xbf4a3f7cbf783f3e,0x3f09bf5f3f7fbf6d,0xbf733f31beacbe16,0x3f80bf653f22be48,0xbe89be603f18bf67,0x3f13bdfbbe953f35,0x3f27bf6f3f80bf5c,
0x3e95bf223f6dbf80,0xbf7f3f62bf0e3e48,0xbef13dc93ec4bf35,0xbf463f75bf7b3f55,0xbf753f46bec40000,0xbdc93ef1bf553f7b,0xbf623f7fbf6d3f35,0x3f22be95be483f0e,
0x3f75bf463ec48000,0x3dc9bef13f55bf7b,0x3f62bf7f3f6dbf35,0xbf223e953e48bf0e,0x3e95bf223f6dbf80,0xbf7f3f62bf0e3e48,0xbef13dc93ec4bf35,0xbf463f75bf7b3f55,
0xbf513f1dbdc9be48,0xbee63f31bf783f80,0xbeb83d973ef1bf35,0xbf5f3f7abf713f4e,0xbf583f77bf753f55,0x3f27becfbe163edb,0xbf803f73bf223ec4,0x3dfb3e2fbf2c3f5c,
0x3f13bf4a3f7fbf7b,0xbf653f39be79bd49,0x3f6fbf7f3f62bf35,0xbefc3e603eacbf18,0xbf093e893e95bf0e,0xbf423f6abf7d3f67,0x3cc9bea13f46bf6d,0xbf7e3f7cbf3e3f04,
0xbf783f80bf553f35,0x3eacbe16bef13f22,0xbf4e3f67bf7b3f6d,0x3f2cbf04bdc93e95,0xbf5c3f3ebe480000,0xbedb3f18bf753f7f,0xbf7d3f71bf0e3ec4,0xbd493e79bf463f62,
0xbe793d493f0ebf35,0xbf713f7dbf623f46,0xbf183edb3e48bec4,0xbf3e3f5cbf7f3f75,0x3f04bf2c3f7bbf80,0xbf673f4ebe953dc9,0x3e16beac3f55bf6d,0xbf803f78bf223ef1,
0xbf423f51bf7f3f7b,0x3f31bf1dbd493e16,0xbf5f3f6abf753f6d,0x3f09bee6be793eac,0xbf733f7abf623f55,0x3eb8be89bedb3f04,0xbf7e3f80bf463f35,0x3e2fbd97bf183f2c,
0xbf273f133dc9be48,0xbf393f4abf803f7d,0xbefc3ecf3e95bec4,0xbf583f65bf783f71,0xbea13e603ef1bf0e,0xbf6f3f77bf673f5c,0xbdfb3cc93f22bf35,0xbf7c3f7fbf4e3f3e,
};
__device__ __align__(1024) uint8_t g_hT[32 * 262144];
__device__ __align__(1024) bf16 g_U[128 * 2 * 8 * 1024];
__device__ __align__(16) uint2 g_gate[2048];
__device__ __align__(16) uint4 g_agg[8 * 1024];
__device__ unsigned g_cnt[8 * 32];
constexpr int CNT_U = 0, CNT_V = 1, CNT_H = 2  , CNT_DONE = 4, CNT_EPOCH = 5;
#define PROFK(i) do { } while (0)
#define PROFC(i) do { } while (0)
#define PROF(i) do { } while (0)
#define PROFG(i) do { } while (0)
#define PROFS(i) do { } while (0)

constexpr int STAGE_BYTES = 49152;
constexpr int OFF_W = 0;
constexpr int OFF_F = 36864;
constexpr int OFF_TW = 45056;
constexpr int OFF_HS = 49152;
constexpr int OFF_A2 = 32768, OFF_B2 = 114688;
constexpr int OFF_U = 4 * STAGE_BYTES;
constexpr int OFF_G = OFF_U + 32768;
constexpr int OFF_BAR = OFF_G + 1024;
constexpr int OFF_REL = OFF_BAR + 272;
constexpr int OFF_GS = OFF_BAR + 304;
constexpr int OFF_DUMMY = OFF_GS + 128;
constexpr int SMEM_BYTES = OFF_DUMMY + 16;
constexpr int BAR_FULL = 0  , BAR_FULL2 = 4  , BAR_X = 9, BAR_U = 10, BAR_W = 11, BAR_H1 = 12, BAR_V = 13,
              BAR_G1 = 14, BAR_HF = 15,
              BAR_H = 16  ,
              BAR_CD = 26, BAR_EMPTY2 = 27  ,
              BAR_C = 32, NBAR = 33;

#define DEVI __device__ __forceinline__
constexpr unsigned SPIN_LIMIT = 1u << 22;

DEVI uint32_t smem_u32(const void* p) { return (uint32_t)__cvta_generic_to_shared(p); }
DEVI uint64_t gtime() { uint64_t t; asm volatile("mov.u64 %0, %%globaltimer;" : "=l"(t)); return t; }
DEVI void mbar_init(uint32_t bar, uint32_t cnt) { asm volatile("mbarrier.init.shared::cta.b64 [%0], %1;" :: "r"(bar), "r"(cnt) : "memory"); }
DEVI void mbar_expect_tx(uint32_t bar, uint32_t bytes) { asm volatile("mbarrier.arrive.expect_tx.shared::cta.b64 _, [%0], %1;" :: "r"(bar), "r"(bytes) : "memory"); }
DEVI void mbar_arrive(uint32_t bar) { asm volatile("mbarrier.arrive.shared::cta.b64 _, [%0];" :: "r"(bar) : "memory"); }
DEVI void mbar_wait(uint32_t bar, uint32_t parity) {
    asm volatile("{\n.reg .pred p;\n.reg .u32 n;\nmov.u32 n, 0;\n"
                 "LW:\nmbarrier.try_wait.parity.shared::cta.b64 p, [%0], %1;\n@p bra LD;\n"
                 "add.u32 n, n, 1;\nsetp.lt.u32 p, n, %2;\n@p bra LW;\nLD:\n}"
                 :: "r"(bar), "r"(parity), "n"(1 << 17) : "memory");
}
DEVI bool elect() {
    uint32_t p;
    asm volatile("{\n.reg .pred P;\nelect.sync _|P, 0xffffffff;\nselp.u32 %0, 1, 0, P;\n}" : "=r"(p));
    return p;
}
DEVI void fence_barrier_init() { asm volatile("fence.mbarrier_init.release.cluster;" ::: "memory"); }
DEVI void fence_proxy_async_smem() { asm volatile("fence.proxy.async.shared::cta;" ::: "memory"); }
DEVI void helper_sync() { asm volatile("bar.sync 1, 128;" ::: "memory"); }

DEVI void wait_counter(const unsigned* p, unsigned target) {
    for (unsigned n = 0;; n++) {
        unsigned v;
        asm volatile("ld.relaxed.gpu.global.u32 %0, [%1];" : "=r"(v) : "l"(p) : "memory");
        if ((int)(v - target) >= 0 || n > SPIN_LIMIT) break;
    }
}
DEVI void signal_counter(unsigned* p) {
    asm volatile("red.relaxed.gpu.global.add.u32 [%0], 1;" :: "l"(p) : "memory");
}

DEVI void tma_load_3d(uint32_t dst, const CUtensorMap* map, uint32_t bar, int c0, int c1, int c2) {
    asm volatile("cp.async.bulk.tensor.3d.shared::cluster.global.mbarrier::complete_tx::bytes [%0], [%1, {%3, %4, %5}], [%2];"
        :: "r"(dst), "l"(map), "r"(bar), "r"(c0), "r"(c1), "r"(c2) : "memory");
}
DEVI void tma_load_4d(uint32_t dst, const CUtensorMap* map, uint32_t bar, int c0, int c1, int c2, int c3) {
    asm volatile("cp.async.bulk.tensor.4d.shared::cluster.global.mbarrier::complete_tx::bytes [%0], [%1, {%3, %4, %5, %6}], [%2];"
        :: "r"(dst), "l"(map), "r"(bar), "r"(c0), "r"(c1), "r"(c2), "r"(c3) : "memory");
}
DEVI void tma_store_5d(const CUtensorMap* map, uint32_t src, int c0, int c4) {
    asm volatile("cp.async.bulk.tensor.5d.global.shared::cta.bulk_group [%0, {%2, %4, %4, %4, %3}], [%1];"
        :: "l"(map), "r"(src), "r"(c0), "r"(c4), "r"(0) : "memory");
}
DEVI void tma_store_4d(const CUtensorMap* map, uint32_t src, int c0, int c1, int c2, int c3) {
    asm volatile("cp.async.bulk.tensor.4d.global.shared::cta.bulk_group [%0, {%2, %3, %4, %5}], [%1];"
        :: "l"(map), "r"(src), "r"(c0), "r"(c1), "r"(c2), "r"(c3) : "memory");
}
DEVI void bulk_load(uint32_t dst, const void* src, uint32_t bytes, uint32_t bar) {
    asm volatile("cp.async.bulk.shared::cluster.global.mbarrier::complete_tx::bytes [%0], [%1], %2, [%3];"
        :: "r"(dst), "l"(src), "r"(bytes), "r"(bar) : "memory");
}
DEVI void bulk_prefetch_l2(const void* src, uint32_t bytes) {
    asm volatile("cp.async.bulk.prefetch.L2.global [%0], %1;" :: "l"(src), "r"(bytes) : "memory");
}
DEVI void tma_store_3d(const CUtensorMap* map, uint32_t src, int c0, int c1, int c2) {
    asm volatile("cp.async.bulk.tensor.3d.global.shared::cta.bulk_group [%0, {%2, %3, %4}], [%1];"
        :: "l"(map), "r"(src), "r"(c0), "r"(c1), "r"(c2) : "memory");
}
DEVI void pause(unsigned n) {
    asm volatile("{\n.reg .pred p;\n.reg .u32 a, b;\nmov.u32 a, %%clock;\n"
                 "LP:\nmov.u32 b, %%clock;\nsub.u32 b, b, a;\nsetp.lt.u32 p, b, %0;\n@p bra LP;\n}" :: "r"(n) : "memory");
}
DEVI void bulk_store(void* dst, uint32_t src, uint32_t bytes) {
    asm volatile("cp.async.bulk.global.shared::cta.bulk_group [%0], [%1], %2;" :: "l"(dst), "r"(src), "r"(bytes) : "memory");
}
DEVI void bulk_commit() { asm volatile("cp.async.bulk.commit_group;" ::: "memory"); }
DEVI void bulk_wait0() { asm volatile("cp.async.bulk.wait_group 0;" ::: "memory"); }

DEVI void wgmma_fence() { asm volatile("wgmma.fence.sync.aligned;" ::: "memory"); }
DEVI void wgmma_commit() { asm volatile("wgmma.commit_group.sync.aligned;" ::: "memory"); }
template<int N> DEVI void wgmma_wait() { asm volatile("wgmma.wait_group.sync.aligned %0;" :: "n"(N) : "memory"); }
template<int N> DEVI void wgmma_wait_all(float (&d)[N]) {
    wgmma_wait<0>();
#pragma unroll
    for (int i = 0; i < N; i++) asm volatile("" : "+f"(d[i]) :: "memory");
}
template<int R> DEVI void reg_alloc() { asm volatile("setmaxnreg.inc.sync.aligned.u32 %0;" :: "n"(R)); }
template<int R> DEVI void reg_dealloc() { asm volatile("setmaxnreg.dec.sync.aligned.u32 %0;" :: "n"(R)); }

DEVI uint64_t make_desc(uint32_t addr, uint32_t lbo, uint32_t sbo, uint32_t mode = 1) {
    return (uint64_t)(((addr & 0x3FFFF) >> 4) | ((lbo >> 4) << 16)) | ((uint64_t)((sbo >> 4) | (mode << 30)) << 32);
}

#define ACC8(a, o) "+f"(a[o+0]), "+f"(a[o+1]), "+f"(a[o+2]), "+f"(a[o+3]), "+f"(a[o+4]), "+f"(a[o+5]), "+f"(a[o+6]), "+f"(a[o+7])
#define ACC32(a, o) ACC8(a, o), ACC8(a, o+8), ACC8(a, o+16), ACC8(a, o+24)

DEVI void wgmma_n256(float (&d)[128], uint64_t da, uint64_t db, int scale_d) {
    asm volatile("{\n.reg .pred p;\nsetp.ne.b32 p, %130, 0;\n"
        "wgmma.mma_async.sync.aligned.m64n256k16.f32.bf16.bf16 "
        "{%0, %1, %2, %3, %4, %5, %6, %7, %8, %9, %10, %11, %12, %13, %14, %15, "
        "%16, %17, %18, %19, %20, %21, %22, %23, %24, %25, %26, %27, %28, %29, %30, %31, "
        "%32, %33, %34, %35, %36, %37, %38, %39, %40, %41, %42, %43, %44, %45, %46, %47, "
        "%48, %49, %50, %51, %52, %53, %54, %55, %56, %57, %58, %59, %60, %61, %62, %63, "
        "%64, %65, %66, %67, %68, %69, %70, %71, %72, %73, %74, %75, %76, %77, %78, %79, "
        "%80, %81, %82, %83, %84, %85, %86, %87, %88, %89, %90, %91, %92, %93, %94, %95, "
        "%96, %97, %98, %99, %100, %101, %102, %103, %104, %105, %106, %107, %108, %109, %110, %111, "
        "%112, %113, %114, %115, %116, %117, %118, %119, %120, %121, %122, %123, %124, %125, %126, %127}, "
        "%128, %129, p, 1, 1, 0, 0;\n}\n"
        : ACC32(d, 0), ACC32(d, 32), ACC32(d, 64), ACC32(d, 96)
        : "l"(da), "l"(db), "r"(scale_d));
}
template<int TB>
DEVI void wgmma_n128(float (&d)[64], uint64_t da, uint64_t db, int scale_d) {
    asm volatile("{\n.reg .pred p;\nsetp.ne.b32 p, %66, 0;\n"
        "wgmma.mma_async.sync.aligned.m64n128k16.f32.bf16.bf16 "
        "{%0, %1, %2, %3, %4, %5, %6, %7, %8, %9, %10, %11, %12, %13, %14, %15, "
        "%16, %17, %18, %19, %20, %21, %22, %23, %24, %25, %26, %27, %28, %29, %30, %31, "
        "%32, %33, %34, %35, %36, %37, %38, %39, %40, %41, %42, %43, %44, %45, %46, %47, "
        "%48, %49, %50, %51, %52, %53, %54, %55, %56, %57, %58, %59, %60, %61, %62, %63}, "
        "%64, %65, p, 1, 1, 1, %67;\n}\n"
        : ACC32(d, 0), ACC32(d, 32)
        : "l"(da), "l"(db), "r"(scale_d), "n"(TB));
}
template<int SCALE_D>
DEVI void wgmma_rs_n128(float (&d)[64], const uint4& a, uint64_t db) {
    asm volatile("{\n.reg .pred p;\nsetp.ne.b32 p, %69, 0;\n"
        "wgmma.mma_async.sync.aligned.m64n128k16.f32.bf16.bf16 "
        "{%0, %1, %2, %3, %4, %5, %6, %7, %8, %9, %10, %11, %12, %13, %14, %15, "
        "%16, %17, %18, %19, %20, %21, %22, %23, %24, %25, %26, %27, %28, %29, %30, %31, "
        "%32, %33, %34, %35, %36, %37, %38, %39, %40, %41, %42, %43, %44, %45, %46, %47, "
        "%48, %49, %50, %51, %52, %53, %54, %55, %56, %57, %58, %59, %60, %61, %62, %63}, "
        "{%64, %65, %66, %67}, %68, p, 1, 1, 1;\n}\n"
        : ACC32(d, 0), ACC32(d, 32)
        : "r"(a.x), "r"(a.y), "r"(a.z), "r"(a.w), "l"(db), "n"(SCALE_D));
}
DEVI void wgmma_n16(float (&d)[8], uint64_t da, uint64_t db) {
    asm volatile("{\n.reg .pred p;\nsetp.ne.b32 p, 0, 0;\n"
        "wgmma.mma_async.sync.aligned.m64n16k16.f32.bf16.bf16 "
        "{%0, %1, %2, %3, %4, %5, %6, %7}, %8, %9, p, 1, 1, 1, 0;\n}\n"
        : ACC8(d, 0)
        : "l"(da), "l"(db));
}
template<int SCALE_D>
DEVI void wgmma_rs_n64(float (&d)[32], const uint32_t (&a)[4], uint64_t db) {
    asm volatile("{\n.reg .pred p;\nsetp.ne.b32 p, %37, 0;\n"
        "wgmma.mma_async.sync.aligned.m64n64k16.f32.bf16.bf16 "
        "{%0, %1, %2, %3, %4, %5, %6, %7, %8, %9, %10, %11, %12, %13, %14, %15, "
        "%16, %17, %18, %19, %20, %21, %22, %23, %24, %25, %26, %27, %28, %29, %30, %31}, "
        "{%32, %33, %34, %35}, %36, p, 1, 1, 0;\n}\n"
        : ACC32(d, 0)
        : "r"(a[0]), "r"(a[1]), "r"(a[2]), "r"(a[3]), "l"(db), "n"(SCALE_D));
}
DEVI void ldsm_x4_t(uint32_t (&r)[4], uint32_t addr) {
    asm volatile("ldmatrix.sync.aligned.m8n8.x4.trans.shared.b16 {%0, %1, %2, %3}, [%4];"
        : "=r"(r[0]), "=r"(r[1]), "=r"(r[2]), "=r"(r[3]) : "r"(addr) : "memory");
}
DEVI void ldsm_x4(uint32_t (&r)[4], uint32_t addr) {
    asm volatile("ldmatrix.sync.aligned.m8n8.x4.shared.b16 {%0, %1, %2, %3}, [%4];"
        : "=r"(r[0]), "=r"(r[1]), "=r"(r[2]), "=r"(r[3]) : "r"(addr) : "memory");
}
DEVI void stsm_x4(uint32_t addr, uint32_t r0, uint32_t r1, uint32_t r2, uint32_t r3) {
    asm volatile("stmatrix.sync.aligned.m8n8.x4.shared.b16 [%0], {%1, %2, %3, %4};"
        :: "r"(addr), "r"(r0), "r"(r1), "r"(r2), "r"(r3) : "memory");
}
DEVI void stsm_x4_t(uint32_t addr, uint32_t r0, uint32_t r1, uint32_t r2, uint32_t r3) {
    asm volatile("stmatrix.sync.aligned.m8n8.x4.trans.shared.b16 [%0], {%1, %2, %3, %4};"
        :: "r"(addr), "r"(r0), "r"(r1), "r"(r2), "r"(r3) : "memory");
}
DEVI uint32_t movm(uint32_t a) { uint32_t d; asm volatile("movmatrix.sync.aligned.m8n8.trans.b16 %0, %1;" : "=r"(d) : "r"(a)); return d; }
DEVI uint32_t pack2(float lo, float hi) { uint32_t d; asm("cvt.rn.bf16x2.f32 %0, %1, %2;" : "=r"(d) : "f"(hi), "f"(lo)); return d; }
DEVI float bf_lo(uint32_t v) { return __uint_as_float(v << 16); }
DEVI float bf_hi(uint32_t v) { return __uint_as_float(v & 0xffff0000u); }
DEVI float bf_round(float v) { return __bfloat162float(__float2bfloat16_rn(v)); }
DEVI uint32_t bf_mul2(uint32_t a, uint32_t b) { uint32_t d; asm("mul.rn.bf16x2 %0, %1, %2;" : "=r"(d) : "r"(a), "r"(b)); return d; }
DEVI uint4 lds128u(uint32_t a) { uint4 v; asm volatile("ld.shared.v4.u32 {%0, %1, %2, %3}, [%4];" : "=r"(v.x), "=r"(v.y), "=r"(v.z), "=r"(v.w) : "r"(a) : "memory"); return v; }
DEVI void sts128u(uint32_t a, uint32_t x, uint32_t y, uint32_t z, uint32_t w) { asm volatile("st.shared.v4.u32 [%0], {%1, %2, %3, %4};" :: "r"(a), "r"(x), "r"(y), "r"(z), "r"(w) : "memory"); }
DEVI uint2 lds64u(uint32_t a) { uint2 v; asm volatile("ld.shared.v2.u32 {%0, %1}, [%2];" : "=r"(v.x), "=r"(v.y) : "r"(a) : "memory"); return v; }
DEVI uint32_t ldg32u(const void* p) { uint32_t v; asm volatile("ld.global.nc.u32 %0, [%1];" : "=r"(v) : "l"(p) : "memory"); return v; }
DEVI void sts64(uint32_t a, float x, float y) { asm volatile("st.shared.v2.f32 [%0], {%1, %2};" :: "r"(a), "f"(x), "f"(y) : "memory"); }
DEVI void sts32(uint32_t a, uint32_t v) { asm volatile("st.shared.u32 [%0], %1;" :: "r"(a), "r"(v) : "memory"); }
DEVI uint32_t lds16(uint32_t a) { uint32_t v; asm volatile("ld.shared.u16 %0, [%1];" : "=r"(v) : "r"(a) : "memory"); return v; }
DEVI void cmul2(uint32_t& x, uint32_t& y, uint32_t c, uint32_t s) {
    asm("{\n.reg .b32 t, u;\nxor.b32 t, %3, 0x80008000;\nmul.rn.bf16x2 t, %1, t;\nmul.rn.bf16x2 u, %1, %2;\n"
        "fma.rn.bf16x2 %1, %0, %3, u;\nfma.rn.bf16x2 %0, %0, %2, t;\n}" : "+r"(x), "+r"(y) : "r"(c), "r"(s));
}
DEVI void sts16(uint32_t a, float v) { asm volatile("st.shared.u16 [%0], %1;" :: "r"(a), "r"(pack2(v, v)) : "memory"); }

DEVI float2 cmul(float2 a, float2 b) { return make_float2(fmaf(a.x, b.x, -a.y * b.y), fmaf(a.x, b.y, a.y * b.x)); }
DEVI float2 cfma(float2 a, float2 b, float2 c) { return make_float2(fmaf(a.x, b.x, fmaf(-a.y, b.y, c.x)), fmaf(a.x, b.y, fmaf(a.y, b.x, c.y))); }
DEVI float2 cadd(float2 a, float2 b) { return make_float2(a.x + b.x, a.y + b.y); }
DEVI float2 csub(float2 a, float2 b) { return make_float2(a.x - b.x, a.y - b.y); }
DEVI void fft4(float2& a, float2& b, float2& c, float2& d) {
    const float2 s0 = cadd(a, c), s1 = csub(a, c), s2 = cadd(b, d), t = csub(b, d), s3 = make_float2(t.y, -t.x);
    a = cadd(s0, s2); b = cadd(s1, s3); c = csub(s0, s2); d = csub(s1, s3);
}

struct Params {
    const bf16 *lam_re, *lam_im, *log_dt, *dskip, *gate_w, *c_re, *c_im, *w_r, *w_i;
    int swapB;
    uint8_t perm[68];
};

DEVI void pace(uint32_t cnt_addr) {
    uint32_t v0, v;
    asm volatile("ld.volatile.shared.u32 %0, [%1];" : "=r"(v0) : "r"(cnt_addr) : "memory");
    const unsigned t0 = clock();
    do {
        __nanosleep(20);
        asm volatile("ld.volatile.shared.u32 %0, [%1];" : "=r"(v) : "r"(cnt_addr) : "memory");
    } while (v == v0 && (unsigned)clock() - t0 < 1300u);
}

DEVI void radix8(uint32_t sb, uint32_t gtab, int hf, int w, int lane, int bar) {
    const uint64_t dg = make_desc(gtab, 128, 256, 0);
    const uint32_t st = sb + OFF_U + hf * 8192 + (lane >> 4) * 16384 + (lane & 7) * 128 + (((2 * w + ((lane >> 3) & 1)) ^ (lane & 7)) << 4);
    float acc[8][8];
    const uint64_t da = make_desc(sb + OFF_U + hf * 8192, 16, 16384);
    wgmma_fence();
#pragma unroll
    for (int i = 0; i < 8; i++) wgmma_n16(acc[i], da + 64 * i, dg);
    wgmma_commit();
    wgmma_wait<0>();
    asm volatile("bar.sync %0, 128;" :: "r"(bar) : "memory");
#pragma unroll
    for (int i = 0; i < 8; i++)
        stsm_x4_t((st ^ ((i & 3) << 4)) + i * 1024,
                  pack2(acc[i][0], acc[i][1]), pack2(acc[i][2], acc[i][3]), pack2(acc[i][4], acc[i][5]), pack2(acc[i][6], acc[i][7]));
}

template<int N> DEVI void c_take(float (&acc)[32], uint32_t (&p)[16]) {
    wgmma_wait<N>();
#pragma unroll
    for (int i = 0; i < 32; i++) asm volatile("" : "+f"(acc[i]) :: "memory");
#pragma unroll
    for (int i = 0; i < 16; i++) p[i] = pack2(acc[2 * i], acc[2 * i + 1]);
}
DEVI void c_mm4(float (&acc)[32], const uint32_t (&a)[4][4], uint64_t df) {
    wgmma_rs_n64<0>(acc, a[0], df);
    wgmma_rs_n64<1>(acc, a[1], df + 2);
    wgmma_rs_n64<1>(acc, a[2], df + 4);
    wgmma_rs_n64<1>(acc, a[3], df + 6);
    wgmma_commit();
}
template<int H> DEVI void c_mm2(float (&acc)[2][32], const uint32_t (&a)[2][2][4], uint64_t df) {
    wgmma_fence();
#pragma unroll
    for (int i = 0; i < 2; i++) {
        wgmma_rs_n64<H>(acc[i], a[i][0], df + 2 * H);
        wgmma_rs_n64<1>(acc[i], a[i][1], df + 2 * H + 4);
        wgmma_commit();
    }
}
DEVI void c_twiddle(uint32_t (&p)[16], uint32_t (&a)[2][2][4], const uint4* tw) {
#pragma unroll
    for (int jp = 0; jp < 2; jp++)
#pragma unroll
        for (int hh = 0; hh < 2; hh++) {
            const uint4 w = tw[hh * 2 + jp];
#pragma unroll
            for (int jl = 0; jl < 2; jl++) {
                const int o = 4 * jp + 2 * jl + hh;
                cmul2(p[o], p[8 + o], jl ? w.z : w.x, jl ? w.w : w.y);
                a[jp][0][2 * hh + jl] = movm(p[o]);
                a[jp][1][2 * hh + jl] = movm(p[8 + o]);
            }
        }
}
template<bool LW> DEVI void c_stage(float (&acc)[2][32], const uint4 (&tw)[8], uint64_t df, uint32_t (&w)[2][4][4], uint32_t wa, uint32_t wm) {
    uint32_t p[16], a0[2][2][4], a1[2][2][4];
    c_take<1>(acc[0], p);
    c_twiddle(p, a0, tw);
    c_take<0>(acc[1], p);
    if (LW) {
#pragma unroll
        for (int j = 0; j < 4; j++) ldsm_x4_t(w[0][j], (j < 2 ? wa : wm) + (j & 1) * 512);
    }
    c_mm2<0>(acc, a0, df);
    c_twiddle(p, a1, tw + 4);
    if (LW) {
#pragma unroll
        for (int j = 0; j < 4; j++) ldsm_x4_t(w[1][j], ((j < 2 ? wa : wm) ^ 32) + (j & 1) * 512);
    }
    c_mm2<1>(acc, a1, df);
}

DEVI void phase_c(uint32_t sb, int mrow, int warp, int lane) {
    PROFC(0);
    const uint64_t df = make_desc(sb + OFF_F, 16, 1024);
    float acc[2][32];
    uint4 tw[8];
    uint32_t w[2][4][4];
    const uint32_t xa = sb + OFF_U + ((lane >> 4) * 4 + ((lane & 7) >> 1)) * 1024 + warp * 128
                      + ((((lane & 1) * 4 + ((lane >> 3) & 1)) ^ warp ^ ((lane >> 1) & 3)) << 4);
    const uint32_t wo = sb + OFF_W + (lane >> 4) * 18432 + (lane & 7) * 64 + ((((lane >> 3) & 1) ^ ((lane >> 1) & 3)) << 4);
    const uint32_t wa = wo + warp * 1152, wm = wo + 9216 + mrow * 1152;
    {
        uint32_t a[2][4][4];
#pragma unroll
        for (int h = 0; h < 2; h++)
#pragma unroll
            for (int s = 0; s < 4; s++) ldsm_x4_t(a[h][s], (xa ^ (h * 32)) + (s & 1) * 8192 + (s >> 1) * 16384);
#pragma unroll
        for (int i = 0; i < 8; i++) tw[i] = lds128u(sb + OFF_TW + lane * 16 + i * 512);
        wgmma_fence();
        c_mm4(acc[0], a[0], df);
        c_mm4(acc[1], a[1], df);
    }
    PROFC(1);
    c_stage<true>(acc, tw, df, w, wa, wm);
    PROFC(2);
#pragma unroll
    for (int h = 0; h < 2; h++) {
        uint32_t p[16], a[4][4];
        c_take<1>(acc[h], p);
#pragma unroll
        for (int j = 0; j < 4; j++)
#pragma unroll
            for (int hh = 0; hh < 2; hh++) {
                cmul2(p[2 * j + hh], p[8 + 2 * j + hh], w[h][j][hh], w[h][j][2 + hh]);
                a[j >> 1][2 * (j & 1) + hh] = p[8 + 2 * j + hh];
                a[2 + (j >> 1)][2 * (j & 1) + hh] = p[2 * j + hh];
            }
        wgmma_fence();
        c_mm4(acc[h], a, df);
    }
    PROFC(3);
    c_stage<false>(acc, tw, df, w, wa, wm);
    PROFC(4);
#pragma unroll
    for (int h = 0; h < 2; h++) {
        uint32_t p[16];
        if (h) c_take<0>(acc[1], p); else c_take<1>(acc[0], p);
#pragma unroll
        for (int s = 0; s < 4; s++)
            stsm_x4_t((xa ^ (h * 32)) + (s & 1) * 8192 + ((s >> 1) ^ 1) * 16384, p[4 * s], p[4 * s + 1], p[4 * s + 2], p[4 * s + 3]);
    }
    PROFC(5);
}

#define PFW0 4
#define PACE_H 350
#define PACE_V 500
#define R8_AT 0
#define PFC0 8
__global__ void __cluster_dims__(2, 1, 1) __launch_bounds__(384, 1)
fused_kernel(const __grid_constant__ CUtensorMap mapB, const __grid_constant__ CUtensorMap mapX,
             const __grid_constant__ CUtensorMap mapXs, const __grid_constant__ CUtensorMap mapU0,
             const __grid_constant__ CUtensorMap mapU2, const __grid_constant__ CUtensorMap mapXe,
             const __grid_constant__ CUtensorMap mapCre, const __grid_constant__ CUtensorMap mapCim,
             const __grid_constant__ CUtensorMap mapV, const __grid_constant__ CUtensorMap mapO,
             const __grid_constant__ CUtensorMap mapH, const __grid_constant__ CUtensorMap mapWr,
             const __grid_constant__ CUtensorMap mapWi,
             const __grid_constant__ Params P) {
    extern __shared__ __align__(1024) uint8_t sm[];
    const uint32_t sb = smem_u32(sm);
    const uint32_t bars = sb + OFF_BAR, prog = sb + OFF_REL + 20;
    const int b = P.perm[blockIdx.x >> 1] * 2 + (blockIdx.x & 1), tid = threadIdx.x, warp = __shfl_sync(0xffffffffu, tid >> 5, 0), lane = tid & 31;
    const bool main_cta = b < 128;
    if (b == 129) return;
    const int b2 = ((b & 6) + ((b >> 4) & 1)) * 16 + (b & 8) + (b >> 5) * 2 + (b & 1);

    const int cls = b == 128 ? 128 : (b & 31) ? (b & 31) + 64 * (b >> 5) : (b == 64 ? 32 : b == 32 ? 64 : b);
    auto g1_stage = [](int it) { return it & 3; };
    auto load_w = [&]() {
        const uint32_t bw = bars + 8 * BAR_W;
        mbar_expect_tx(bw, 49152);
#pragma unroll
        for (int i = 0; i < 4; i++)
            tma_load_3d(sb + OFF_W + (i >> 1) * 9216 + (i & 1) * 18432, &mapWr + (i & 1), bw, 0, (1026 * (i < 2 ? cls : (256 - cls) & 255)) >> 7, 0);
        bulk_load(sb + OFF_F, c_tab + 2048, 12288, bw);
    };
    auto load_g1 = [&](int it, int sg) {
        const uint32_t full = bars + 8 * (BAR_FULL + sg), st = sb + sg * STAGE_BYTES;
        mbar_expect_tx(full, STAGE_BYTES);
        tma_load_4d(st, &mapB, full, it * 64, 0, 0, (b & 15) * 8);
        tma_load_4d(st + 16384, &mapX, full, it * 64, 0, 0, (b >> 4) * 128);
    };
    auto load_c = [&](int k, int s) {
        const uint32_t full = bars + 8 * (BAR_FULL2 + s);
        mbar_expect_tx(full, 32768);
        tma_load_3d(sb + OFF_B2 + s * 16384, &mapCre + (k >> 4), full, 0, k < 32 ? (b2 & 14) * 64 : (k & 15) * 64, k < 32 ? k & 15 : b2 & ~1);
    };
    auto load_h = [&](int k, int s) {
        const uint8_t* src = k < 32 ? g_hT + (k * 8 + (b2 >> 4)) * 32768 : (const uint8_t*)c_inv + (k - 32) * 32768;
        bulk_load(sb + OFF_A2 + s * 16384, src + (b & 1) * 16384, 16384, bars + 8 * (BAR_FULL2 + s));
    };
    if (elect()) {
        asm volatile("prefetch.tensormap [%0];" :: "l"(&mapB + warp) : "memory");
        if (warp == 11) PROFG(0);
        if (warp == 8) {
            PROF(0);
#pragma unroll
            for (int i = 0; i < NBAR; i++) mbar_init(bars + 8 * i, i < BAR_G1 ? 1 : i < BAR_H ? 2 : i < BAR_CD ? 4 : i < BAR_C ? 8 : 128);
            *(uint4*)(sm + OFF_REL) = make_uint4(0, 0, 0, 0);
            *(uint2*)(sm + OFF_REL + 16) = make_uint2(0, 0);
            fence_barrier_init();
            fence_proxy_async_smem();
            if (main_cta) {
#pragma unroll 1
                for (int it = 0; it < 4; it++) load_g1(it, it);
            } else load_w();
            PROF(27);
        }
    }
    __syncthreads();
    auto load_epoch = [&]() {
        unsigned e;
        asm volatile("ld.relaxed.gpu.global.u32 %0, [%1];" : "=r"(e) : "l"(&g_cnt[CNT_EPOCH * 32]));
        return e + 1;
    };
    const int g = lane >> 2, q = lane & 3;

    if (warp < 8) {
        reg_alloc<192>();
        if (tid == 0) PROF(28);
        if (tid == 224) PROFG(8);
        const int wg = warp >> 2;
        unsigned epoch = 0;
        auto release = [&](int s) -> bool {
            if (warp & 3) return false;
            unsigned old = 0;
            if (elect()) asm volatile("atom.relaxed.cta.shared.inc.u32 %0, [%1], 1;" : "=r"(old) : "r"(sb + OFF_REL + 4 * s) : "memory");
            return __any_sync(0xffffffffu, old == 1);
        };
        if (main_cta) {
            float acc[128];
            const int tc = b >> 4;
            const int pp = (b & 15) * 64 + (tid >> 2);
            const bf16 lr_ = P.lam_re[pp], li_ = P.lam_im[pp], ld_ = P.log_dt[pp];
            const int gn = 16 * (b & 15) + 2 * warp + (lane >> 4);
            const uint32_t goff = 16384 + gn * 128 + ((((lane & 15) >> 1) ^ (gn & 7)) << 4) + (lane & 1) * 8;
            const uint2* gwp = (const uint2*)P.gate_w + (lane & 15);
            uint2 gw = __ldg(gwp);
            float gs = 0.f;
            float2 lam1, lam8, lam64, lam128, wq, w4, l64q;
            float m00, m01, m10, m11, sg2;
#pragma unroll 1
            for (int it = 0; it < 16; it++) {
                const int sg = g1_stage(it);
                mbar_wait(bars + 8 * (BAR_FULL + sg), (it >> 2) & 1);
                if (tid == 0) PROFK(it);
                const uint32_t st = sb + sg * STAGE_BYTES;
                const uint64_t da = make_desc(st + wg * 8192, 16, 1024), db = make_desc(st + 16384, 16, 1024);
                uint2 xv = lds64u(st + goff);
                wgmma_fence();
#pragma unroll
                for (int j = 0; j < 4; j++) wgmma_n256(acc, da + 2 * j, db + 2 * j, (it | j) != 0);
                wgmma_commit();
                xv.x = bf_mul2(xv.x, gw.x); xv.y = bf_mul2(xv.y, gw.y);
                gs += (bf_lo(xv.x) + bf_hi(xv.x)) + (bf_lo(xv.y) + bf_hi(xv.y));
                gw = __ldg(gwp + ((it + 1) & 15) * 16);
                wgmma_wait<1>();
                if (it > 0 && it < 14 && release(g1_stage(it - 1)) && elect()) {
                    if (it == 13) load_w();
                    else load_g1(it + 3, g1_stage(it - 1));
                    asm volatile("st.volatile.shared.u32 [%0], %1;" :: "r"(prog), "r"(it) : "memory");
                }
                if (warp == 1 && elect()) {
                    if ((unsigned)(it - PFW0) < 4) bulk_prefetch_l2(((it & 1) ? P.w_i : P.w_r) + (size_t)(2 * b + (((it - PFW0) >> 1) & 1)) * 4104, 8208);
                    if ((unsigned)(it - PFC0) < 8) bulk_prefetch_l2(((b & 1) ? P.c_im : P.c_re) + (size_t)(b >> 1) * 16384 + (it - PFC0) * 2048, 4096);
                }
                __syncwarp();
            }
            reg_alloc<200>();
            epoch = load_epoch();
            {
                const float lr = __bfloat162float(lr_), li = __bfloat162float(li_);
                const float dt = bf_round(expf(__bfloat162float(ld_)));
                const float mag = expf(dt * lr);
                float sn, cs; sincospif(dt * li * 0.31830988618379067f, &sn, &cs);
                lam1 = make_float2(mag * cs, mag * sn);
                const float inv = 1.f / (lr * lr + li * li);
                const float2 coef = cmul(make_float2(lam1.x - 1.f, lam1.y), make_float2(lr * inv, -li * inv));
                m00 = coef.x; m01 = -coef.y; m10 = -coef.y; m11 = -coef.x; sg2 = -1.f;
                if (P.swapB) { lam1.y = -lam1.y; m00 = -coef.y; m01 = coef.x; m10 = -coef.x; m11 = -coef.y; sg2 = 1.f; }
                float2 z = cmul(lam1, lam1);
                z = cmul(z, z); lam8 = cmul(z, z);
                z = cmul(lam8, lam8); z = cmul(z, z);
                lam64 = cmul(z, z); lam128 = cmul(lam64, lam64);
                const float2 l256 = cmul(lam128, lam128), l512 = cmul(l256, l256);
                w4 = cmul(l512, l512);
                const float2 one = make_float2(1.f, 0.f);
                wq = cmul((q & 1) ? l256 : one, (q & 2) ? l512 : one);
                l64q = cmul((q & 1) ? lam64 : one, (q & 2) ? lam128 : one);
            }
#pragma unroll
            for (int o = 1; o < 16; o <<= 1) gs += __shfl_xor_sync(0xffffffffu, gs, o);
            {
                const float gg = bf_round(__fdividef(1.f, 1.f + __expf(-bf_round(gs))));
                if ((lane & 15) == 0) *(uint2*)(sm + OFF_GS + (2 * warp + (lane >> 4)) * 8) = make_uint2(__float_as_uint(gg), __float_as_uint(2.f * bf_round(1.f - gg)));
            }
            const uint4 *ap = &g_agg[(tc - 1 - q) * 1024 + pp], *ap1 = q + 5 <= tc ? ap - 4096 : ap;
            if (q + 5 > tc) w4 = make_float2(0.f, 0.f);
            asm volatile("st.volatile.shared.v4.f32 [%0], {%1, %2, %3, %4};" :: "r"(sb + OFF_DUMMY), "f"(lam64.x + lam128.x + w4.x), "f"(wq.x + l64q.x + m00),
                         "f"(lam64.y + lam128.y + w4.y), "f"(wq.y + l64q.y + m01 + __uint_as_float((uint32_t)(size_t)ap1)) : "memory");
            wgmma_wait_all(acc);
            if ((tid & 127) == 0) mbar_arrive(bars + 8 * BAR_G1);
            if (tid == 0) PROF(3);
            if (tid == 128) PROF(25);
            if (tid == 224) PROFG(12);
            PROFS(0);
            float2 ag[8];
#pragma unroll
            for (int c = 0; c < 8; c++) ag[c] = make_float2(acc[16 * c], acc[16 * c + 2]);
#pragma unroll
            for (int r = 1; r < 8; r++)
#pragma unroll
                for (int c = 0; c < 8; c++) {
                    const int i = 16 * c + 4 * (r >> 1) + (r & 1);
                    ag[c] = cfma(lam1, ag[c], make_float2(acc[i], acc[i + 2]));
                }
            float2 v = ag[0];
#pragma unroll
            for (int c = 1; c < 8; c++) v = cfma(lam8, v, ag[c]);
            {
                float2 n = make_float2(__shfl_up_sync(0xffffffffu, v.x, 1, 4), __shfl_up_sync(0xffffffffu, v.y, 1, 4));
                if (q >= 1) v = cfma(lam64, n, v);
                n = make_float2(__shfl_up_sync(0xffffffffu, v.x, 2, 4), __shfl_up_sync(0xffffffffu, v.y, 2, 4));
                if (q >= 2) v = cfma(lam128, n, v);
            }
            if (q == 3 && tc < 7) {
                asm volatile("st.relaxed.gpu.global.v4.u32 [%0], {%1, %2, %3, %4};"
                    :: "l"(ap + 4096), "r"(__float_as_uint(v.x)), "r"(epoch), "r"(__float_as_uint(v.y)), "r"(epoch) : "memory");
            }
            uint4 r0, r1;
            auto poll = [&]() {
                asm volatile("ld.relaxed.gpu.global.v4.u32 {%0, %1, %2, %3}, [%8];\n"
                             "ld.relaxed.gpu.global.v4.u32 {%4, %5, %6, %7}, [%9];"
                    : "=r"(r0.x), "=r"(r0.y), "=r"(r0.z), "=r"(r0.w), "=r"(r1.x), "=r"(r1.y), "=r"(r1.z), "=r"(r1.w) : "l"(ap), "l"(ap1) : "memory");
            };
            if (q < tc) poll();
            PROFS(1);
            float2 ex = make_float2(__shfl_up_sync(0xffffffffu, v.x, 1, 4), __shfl_up_sync(0xffffffffu, v.y, 1, 4));
            if (q == 0) ex = make_float2(0.f, 0.f);
            {
                uint32_t z;
                asm volatile("ld.volatile.shared.u32 %0, [%1];" : "=r"(z) : "r"(prog) : "memory");
                z >>= 16;
                m00 = __uint_as_float(__float_as_uint(m00) | z); m01 = __uint_as_float(__float_as_uint(m01) | z);
                m10 = __uint_as_float(__float_as_uint(m10) | z); m11 = __uint_as_float(__float_as_uint(m11) | z);
            }
            auto scale = [&](float& x, float& y) { const float u = fmaf(m00, x, m01 * y); y = fmaf(m10, x, m11 * y); x = u; };
#pragma unroll
            for (int i = 0; i < 128; i += 4) { scale(acc[i], acc[i + 2]); scale(acc[i + 1], acc[i + 3]); }
#pragma unroll
            for (int c = 0; c < 7; c++) { scale(ag[c].x, ag[c].y); asm volatile("" : "+f"(ag[c].x), "+f"(ag[c].y)); }
#pragma unroll
            for (int i = 0; i < 128; i++) asm volatile("" : "+f"(acc[i]));
            {
                float2 part = make_float2(0.f, 0.f);
                PROFS(2);
                if (q < tc) {
                    for (unsigned n = 0; (r0.y != epoch || r0.w != epoch || r1.y != epoch || r1.w != epoch) && n < SPIN_LIMIT; n++) poll();
                    part = cfma(w4, make_float2(__uint_as_float(r1.x), __uint_as_float(r1.z)), make_float2(__uint_as_float(r0.x), __uint_as_float(r0.z)));
                    part = cmul(wq, part);
                }
                __syncwarp();
                part.x += __shfl_xor_sync(0xffffffffu, part.x, 1); part.y += __shfl_xor_sync(0xffffffffu, part.y, 1);
                part.x += __shfl_xor_sync(0xffffffffu, part.x, 2); part.y += __shfl_xor_sync(0xffffffffu, part.y, 2);
                ex = cfma(l64q, part, ex);
            }
            if (tid == 0) PROF(4);
            PROFS(3);
            scale(ex.x, ex.y);
            lam1.y *= sg2; lam8.y *= sg2;
#pragma unroll
            for (int c = 0; c < 8; c++) { const float2 n = cfma(lam8, ex, ag[c]); ag[c] = ex; ex = n; }
            mbar_wait(bars + 8 * BAR_G1, 0);
#pragma unroll
            for (int r = 0; r < 8; r++) {
#pragma unroll
                for (int c = 0; c < 8; c++) {
                    const int i = 16 * c + 4 * (r >> 1) + (r & 1);
                    ag[c] = cfma(lam1, ag[c], make_float2(acc[i], acc[i + 2]));
                }
                const uint32_t hs = sb + OFF_HS + wg * 14336 + ((tid * 16) ^ ((tid << 1) & 48)) + r * 2048;
                sts128u(hs + 32768, pack2(ag[0].x, ag[4].x), pack2(ag[1].x, ag[5].x), pack2(ag[2].x, ag[6].x), pack2(ag[3].x, ag[7].x));
                sts128u(hs, pack2(ag[0].y, ag[4].y), pack2(ag[1].y, ag[5].y), pack2(ag[2].y, ag[6].y), pack2(ag[3].y, ag[7].y));
                if (r & 1) {
                    fence_proxy_async_smem();
                    __syncwarp();
                    if (lane == 0) mbar_arrive(bars + 8 * (BAR_H + 5 * wg + (r >> 1)));
                }
            }
            if (tid == 0) PROF(5);
            PROFS(4);
        }
        mbar_wait(bars + 8 * BAR_C, 0);
        if (tid == 0) PROF(6);
        PROFS(5);
        phase_c(sb, b == 0 ? (8 - warp) & 7 : 7 - warp, warp, lane);
        fence_proxy_async_smem();
        __syncwarp();
        if (lane == 0) mbar_arrive(bars + 8 * BAR_CD);
        if (tid == 0) PROF(7);
        PROFS(6);
        PROFC(6);
        {
            float acc[64], acc2[64];
            uint32_t dk[16];
#pragma unroll
            for (int j = 0; j < 16; j++) dk[j] = ldg32u(P.dskip + (b2 & 14) * 64 + 2 * q + 8 * j);
            const int trow = 64 * (16 * (b & 1) + 2 * warp) + 32 * (g & 1) + 8 * (g >> 1) + (b2 >> 4);
            int s = 3, sp = 0, k = 0; uint32_t ph = 0;
            auto steps = [&](int lim) {
#pragma unroll 1
                for (; k < lim; k++) {
                    mbar_wait(bars + 8 * (BAR_FULL2 + s), ph);
                    if (tid == 0 && k == 0) PROF(16);
                    if (tid == 0 && (k & 1) == 0) PROFK(16 + (k >> 1));
                    const uint64_t da = make_desc(sb + OFF_A2 + s * 16384 + wg * 8192, 4096, 512, 2), db = make_desc(sb + OFF_B2 + s * 16384, 16, 1024);
                    wgmma_fence();
#pragma unroll
                    for (int j = 0; j < 4; j++) wgmma_n128<0>(acc, da + 64 * j, db + 2 * j, (k | j) != 0);
                    wgmma_commit();
                    wgmma_wait<1>();
                    if (k > 0 && lane == 0) mbar_arrive(bars + 8 * (BAR_EMPTY2 + sp));
                    __syncwarp();
                    sp = s;
                    if (s == 2) ph ^= 1;
                    if (++s == 5) s = 0;
                }
            };
            steps(main_cta ? R8_AT + 2 * wg : 0);
            mbar_wait(bars + 8 * BAR_CD, 0);
            radix8(sb, sb + OFF_G + 512, wg, warp & 3, lane, 5 + wg);
            fence_proxy_async_smem();
            __syncwarp();
            if (lane == 0) mbar_arrive(bars + 8 * (BAR_H + 5 * wg + 4));
            if (tid == 0) PROF(24);
            if (tid == 224) PROFG(16);
            if (main_cta) {
            steps(32);
            const float2* gp = (const float2*)&g_gate[(trow & ~255) + ((trow & 62) << 2) + ((trow >> 5) & 6) + (trow & 1)];
            const float2 g0 = __ldcg(gp), g1 = __ldcg(gp + 2);
            if (wg) asm volatile("bar.sync 3, 256;" ::: "memory");
#pragma unroll
            for (int k = 0; k < 4; k++) {
                const int s = k;
                mbar_wait(bars + 8 * (BAR_FULL2 + s), k == 3);
                const uint64_t da = make_desc(sb + OFF_A2 + s * 16384 + wg * 8192, 4096, 512, 2), db = make_desc(sb + OFF_B2 + s * 16384, 8192, 1024);
                wgmma_fence();
#pragma unroll
                for (int j = 0; j < 4; j++) wgmma_n128<1>(acc2, da + 64 * j, db + 128 * j, (k | j) != 0);
                wgmma_commit();
            }
            if (!wg) asm volatile("bar.arrive 3, 256;" ::: "memory");
            const uint32_t ob = sb + (wg ? 0 : OFF_U) + (warp & 3) * 8192, rr = 2 * (g & 3) + (g >> 2);
            const uint32_t xrow = 4 * (lane & 1) + ((lane >> 1) & 3);
            const uint32_t xb = sb + wg * 16384 + ((warp & 3) * 16 + (lane & 8) + xrow) * 128 + (((lane >> 4) ^ xrow) << 4);
            wgmma_wait<4>();
#pragma unroll
            for (int i = 0; i < 64; i++) asm volatile("" : "+f"(acc[i]) :: "memory");
            mbar_wait(bars + 8 * BAR_X, 1);
#pragma unroll
            for (int j = 0; j < 16; j += 2) {
                uint32_t xv[4];
                ldsm_x4(xv, (xb ^ ((j & 7) << 4)) + (j >> 3) * 8192);
#pragma unroll
                for (int i = 0; i < 4; i++) {
                    const uint32_t p = bf_mul2(xv[i], dk[j + (i >> 1)]);
                    const float sc = (i & 1) ? g1.y : g0.y;
                    acc[4 * j + 2 * i] = sc * fmaf(bf_lo(p), 0.5f, acc[4 * j + 2 * i]);
                    acc[4 * j + 2 * i + 1] = sc * fmaf(bf_hi(p), 0.5f, acc[4 * j + 2 * i + 1]);
                }
            }
            if (wg) asm volatile("bar.sync 4, 256;" ::: "memory");
            else asm volatile("bar.arrive 4, 256;" ::: "memory");
            wgmma_wait_all(acc2);
            if (tid == 0) PROF(17);
            if (tid == 128) PROF(18);
            if (tid == 224) PROFG(20);
            const uint32_t oa = ob + rr * 128 + (((q >> 1) ^ rr) << 4) + (q & 1) * 8;
#pragma unroll
            for (int c = 0; c < 4; c++) {
#pragma unroll
                for (int j = 0; j < 4; j++) {
                    const int i = 16 * c + 4 * j;
                    sts64((oa ^ (j << 5)) + c * 2048, fmaf(g0.x, acc2[i], acc[i]), fmaf(g0.x, acc2[i + 1], acc[i + 1]));
                    sts64((oa ^ (j << 5)) + c * 2048 + 1024, fmaf(g1.x, acc2[i + 2], acc[i + 2]), fmaf(g1.x, acc2[i + 3], acc[i + 3]));
                }
                fence_proxy_async_smem();
                __syncwarp();
                if (elect()) tma_store_5d(&mapO, ob + c * 2048, (b2 >> 4) * 1024 + (b2 & 14) * 64 + 32 * c, 16 * (b & 1) + 2 * warp);
            }
            if (elect()) {
                bulk_commit();
                asm volatile("cp.async.bulk.wait_group.read 0;" ::: "memory");
            }
            if (tid == 0) PROF(19);
            if (tid == 224) { PROF(20); PROFG(4); }
            }
        }
        if (tid == 0) {
            const unsigned old = atomicAdd(&g_cnt[CNT_DONE * 32], 1u);
            if (old == 128) { g_cnt[CNT_DONE * 32] = 0; g_cnt[CNT_EPOCH * 32] = load_epoch(); }
        }
    } else {
        reg_dealloc<120>();
        const int t = tid - 256, w = warp - 8;
        if (w == 0 && main_cta && elect()) {
            mbar_expect_tx(bars + 8 * BAR_X, 32768);
            tma_load_4d(sb + OFF_U, &mapXs, bars + 8 * BAR_X, (b & 15) * 64, 0, 0, b >> 4);
            tma_load_4d(sb + OFF_U + 16384, &mapXs, bars + 8 * BAR_X, (b & 15) * 64 + 32, 0, 0, b >> 4);
            asm volatile("prefetch.tensormap [%0];" :: "l"(&mapWi) : "memory");
        }
        const unsigned epoch = load_epoch();
        const bool real_cls = (cls & 127) == 0;
        const bool special = t < 4;
        const float R = 0.70710678118654752f;
        uint4 fa[4];
#pragma unroll
        for (int i = 0; i < 4; i++) fa[i] = __ldg((const uint4*)c_tab + i * 128 + t);
        float2 w1, w2, w3;
        {
            const int kk = (t >> 3) & 7, r = t & 7;
            float sn, cs;
            sincospif((float)(((cls + 256 * kk) * r) & 2047) * (1.f / 1024.f), &sn, &cs);
            sn *= 1.f / 1024.f; cs *= 1.f / 1024.f;
            const uint32_t gf = sb + OFF_G + kk * 16 + r * 2, gi = sb + OFF_G + 512 + r * 16 + kk * 2;
            if (t < 64) {
                sts16(gf, cs); sts16(gf + 128, real_cls ? 0.f : sn); sts16(gf + 256, -sn); sts16(gf + 384, real_cls ? 0.f : cs);
                sts16(gi, cs); sts16(gi + 128, -sn); sts16(gi + 256, sn); sts16(gi + 384, cs);
            }
            sincospif((float)(8 * w + g) * (1.f / 128.f), &sn, &cs);
            w1 = make_float2(cs, -sn); w2 = cmul(w1, w1); w3 = cmul(w1, w2);
        }
        if (main_cta) {
            const uint32_t ua = sb + OFF_U + (lane >> 4) * 8192 + (8 * w + (lane & 7)) * 64 + ((((lane >> 3) & 1) ^ ((lane >> 1) & 3)) << 4);
            mbar_wait(bars + 8 * BAR_X, 0);
            if (t == 0) PROF(8);
#pragma unroll 1
            for (int hf = 0; hf < 2; hf++) {
                float acc[64];
                const uint64_t db = make_desc(sb + OFF_U + hf * 16384, 4096, 512, 2);
                wgmma_fence();
                wgmma_rs_n128<0>(acc, fa[0], db); wgmma_rs_n128<1>(acc, fa[1], db + 64); wgmma_rs_n128<1>(acc, fa[2], db + 128); wgmma_rs_n128<1>(acc, fa[3], db + 192);
                wgmma_commit();
                wgmma_wait_all(acc);
                helper_sync();
#pragma unroll
                for (int jp = 0; jp < 2; jp++) {
                    float2 y[4][4];
#pragma unroll
                    for (int i = 0; i < 4; i++) {
                        const int o = 8 * jp + 4 * (i >> 1) + (i & 1);
#pragma unroll
                        for (int m = 0; m < 4; m++) y[i][m] = make_float2(acc[16 * m + o], acc[16 * m + o + 2]);
                    }
                    if (special) {
#pragma unroll
                        for (int i = 0; i < 4; i++) {
                            const float2 s0 = cadd(y[i][0], y[i][2]), s1 = csub(y[i][0], y[i][2]), s2 = cadd(y[i][1], y[i][3]), s3 = csub(y[i][1], y[i][3]);
                            const float b0 = y[i][0].y, b2 = y[i][2].y;
                            y[i][0] = make_float2(s0.x + s2.x, s0.x - s2.x);
                            y[i][1] = make_float2(s1.x, -s3.x);
                            y[i][2] = make_float2(fmaf(R, s3.y, b0), fmaf(-R, s2.y, -b2));
                            y[i][3] = make_float2(fmaf(-R, s3.y, b0), fmaf(-R, s2.y, b2));
                        }
                    } else {
#pragma unroll
                        for (int i = 0; i < 4; i++) {
                            y[i][1] = cmul(y[i][1], w1); y[i][2] = cmul(y[i][2], w2); y[i][3] = cmul(y[i][3], w3);
                            fft4(y[i][0], y[i][1], y[i][2], y[i][3]);
                        }
                    }
                    __syncwarp();
#pragma unroll
                    for (int c = 0; c < 4; c++)
                        stsm_x4((ua ^ (jp * 32)) + hf * 16384 + c * 2048, pack2(y[0][c].x, y[1][c].x), pack2(y[2][c].x, y[3][c].x),
                                pack2(y[0][c].y, y[1][c].y), pack2(y[2][c].y, y[3][c].y));
                }
                fence_proxy_async_smem();
                helper_sync();
                if (w == 0 && elect()) {
                    tma_store_4d(&mapU0, sb + OFF_U + hf * 16384, (b & 15) * 64 + hf * 32, 0, 0, b >> 4);
                    bulk_commit();
                }
            }
        }
        reg_dealloc<104>();
        if (w == 0 && elect()) {
            PROF(21);
            if (main_cta) {
                bulk_wait0();
                signal_counter(&g_cnt[CNT_U * 32]);
            }
            PROF(9);
            mbar_expect_tx(bars + 8 * BAR_U, 32768);
            wait_counter(&g_cnt[CNT_U * 32], epoch * 128);
            PROF(11);
#pragma unroll 1
            for (int i = 0; i < 2; i++) {
#pragma unroll
                for (int j = 0; j < 4; j++)
                    tma_load_4d(sb + OFF_U + i * 16384 + j * 4096, &mapU2, bars + 8 * BAR_U, 0, 0, j * 4, b == 128 ? 1 : b == 0 ? 0 : 2 * b + i);
            }
        }
        fence_proxy_async_smem();
        helper_sync();
        mbar_wait(bars + 8 * BAR_U, 0);
        if (t == 0) PROF(23);
#pragma unroll 1
        for (int hf = 0; hf < 2; hf++) radix8(sb, sb + OFF_G, hf, w, lane, 1);
        if (t == 0) PROF(22);
        mbar_wait(bars + 8 * BAR_W, 0);
        if (t == 0) PROF(10);
#pragma unroll 1
        for (int rr = 0; rr < 2; rr++) {
            const int row = 2 * w + rr;
            const uint32_t dp = sb + OFF_W + row * 1152, mp = sb + OFF_W + 9216 + (b == 0 ? (8 - row) & 7 : 7 - row) * 1152;
            const uint32_t od = dp + ((1026 * cls) & 127), om = mp + ((1026 * (256 - cls)) & 127);
            uint32_t v[2][16][2], e[2][2];
#pragma unroll
            for (int pl = 0; pl < 2; pl++) {
#pragma unroll
                for (int i = 0; i < 8; i++) {
                    const uint32_t a = od + 4 * lane + pl * 18432 + 128 * i, c = om - 4 * lane + pl * 18432 + 1024 - 128 * i;
                    v[pl][i][0] = lds16(a); v[pl][i][1] = lds16(a + 2);
                    v[pl][8 + i][0] = lds16(c); v[pl][8 + i][1] = lds16(c - 2);
                }
                e[pl][0] = lds16(om + pl * 18432); e[pl][1] = lds16(od + pl * 18432 + 1024);
            }
            __syncwarp();
#pragma unroll
            for (int pl = 0; pl < 2; pl++) {
                if (lane == 0) {
                    v[pl][0][0] = pack2(fmaf(pl ? -0.5f : 0.5f, bf_lo(e[pl][0]), 0.5f * bf_lo(v[pl][0][0])), 0.f);
                    v[pl][8][0] = pack2(fmaf(pl ? -0.5f : 0.5f, bf_lo(e[pl][1]), 0.5f * bf_lo(v[pl][8][0])), 0.f);
                }
#pragma unroll
                for (int i = 0; i < 16; i++)
                    sts32((i < 8 ? dp : mp) + pl * 18432 + (i & 7) * 128 + ((lane * 4) ^ ((i & 3) << 4)),
                          __byte_perm(v[pl][i][0], v[pl][i][1], 0x5410) ^ (pl && i >= 8 ? 0x80008000u : 0u));
            }
        }
        mbar_arrive(bars + 8 * BAR_C);
        if (t == 0) PROF(12);
        if (elect()) {
            if ((w & 1) == 0) {
                const int hf = w >> 1;
                const uint32_t bh = bars + 8 * (BAR_H + 5 * hf);
                if (main_cta) {
#pragma unroll
                    for (int i = 0; i < 8; i++) {
                        if (i < 4) mbar_wait(bh + 8 * i, 0);
                        if (i > 4) pause(PACE_H);
                        if (i == 0 && hf) PROF(29);
                        if (i == 3 && hf) PROF(30);
                        tma_store_3d(&mapH, sb + OFF_HS + (i < 4 ? 32768 : 0) + hf * 16384 + (i & 3) * 4096, 0, (b >> 4) * 2 + hf, (i >> 2) * 128 + (b & 15) * 8 + (i & 3) * 2);
                        if (i == 0) bulk_store(g_gate + 16 * b + 8 * hf, sb + OFF_GS + 64 * hf, 64);
                        if ((i & 3) == 3) {
                            bulk_commit();
                            bulk_wait0();
                            signal_counter(&g_cnt[(CNT_H + (i >> 2)) * 32]);
                            if (hf) PROF(i < 4 ? 26 : 2);
                        }
                    }
                    mbar_arrive(bars + 8 * BAR_HF);
                }
                mbar_wait(bh + 32, 0);
#pragma unroll
                for (int i = 0; i < 4; i++) {
                    if (i == 2 && real_cls) break;
                    if (i) pause(PACE_V);
                    tma_store_4d(&mapU2, sb + OFF_U + (i >> 1) * 16384 + hf * 8192 + (i & 1) * 4096, 0, 0, hf * 8 + (i & 1) * 4, b == 128 ? 1 : 2 * b + (i >> 1));
                }
                bulk_commit();
                bulk_wait0();
                signal_counter(&g_cnt[CNT_V * 32]);
                if (hf) PROF(13);
            } else if (main_cta && w == 1) {
                mbar_wait(bars + 8 * BAR_G1, 0);
#pragma unroll 1
                for (int k = 0; k < 5; k++) load_c(k, k < 2 ? k + 3 : k - 2);
                wait_counter(&g_cnt[CNT_H * 32], epoch * 256);
                PROF(1);
#pragma unroll
                for (int k = 0; k < 5; k++) {
                    if (k == 2) mbar_wait(bars + 8 * BAR_CD, 0);
                    if (k == 3) mbar_wait(bars + 8 * BAR_HF, 0);
                    load_h(k, k < 2 ? k + 3 : k - 2);
                }
                int s = 3; uint32_t ph = 0;
#pragma unroll 1
                for (int k = 5; k < 36; k++) {
                    if ((k & 15) == 0) mbar_wait(bars + 8 * (BAR_H1 - 1 + (k >> 4)), 0);
                    mbar_wait(bars + 8 * (BAR_EMPTY2 + s), ph);
                    load_c(k, s);
                    load_h(k, s);
                    if (s == 2) ph ^= 1;
                    if (++s == 5) s = 0;
                }
            } else if (main_cta) {
                bulk_prefetch_l2(c_inv + b * 128, 1024);
                mbar_wait(bars + 8 * BAR_CD, 0);
                mbar_expect_tx(bars + 8 * BAR_X, 32768);
                tma_load_3d(sb, &mapXe, bars + 8 * BAR_X, 0, 128 * (b & 1), b2 & ~1);
                tma_load_3d(sb + 16384, &mapXe, bars + 8 * BAR_X, 0, 128 * (b & 1) + 64, b2 & ~1);
                wait_counter(&g_cnt[(CNT_H + 1) * 32], epoch * 256);
                mbar_arrive(bars + 8 * BAR_H1);
                wait_counter(&g_cnt[CNT_V * 32], epoch * 258);
                mbar_arrive(bars + 8 * BAR_V);
                PROF(14);
            }
        }
    }
}

typedef CUresult (*PFN_encodeTiled)(CUtensorMap*, CUtensorMapDataType, cuuint32_t, void*, const cuuint64_t*, const cuuint64_t*,
                                    const cuuint32_t*, const cuuint32_t*, CUtensorMapInterleave, CUtensorMapSwizzle,
                                    CUtensorMapL2promotion, CUtensorMapFloatOOBfill);

static CUtensorMap make_map(PFN_encodeTiled enc, const void* ptr, int rank, const cuuint64_t* dims, const cuuint64_t* strides, const cuuint32_t* box,
                            CUtensorMapSwizzle sw = CU_TENSOR_MAP_SWIZZLE_128B, CUtensorMapDataType dt = CU_TENSOR_MAP_DATA_TYPE_BFLOAT16) {
    CUtensorMap m;
    cuuint32_t es[5] = {1, 1, 1, 1, 1};
    enc(&m, dt, rank, (void*)ptr, dims, strides, box, es, CU_TENSOR_MAP_INTERLEAVE_NONE,
        sw, CU_TENSOR_MAP_L2_PROMOTION_L2_128B, CU_TENSOR_MAP_FLOAT_OOB_FILL_NONE);
    return m;
}

extern "C" void kernel_launch(void* const* d_in, const int* in_sizes, int n_in, void* d_out, int out_size) {
    const bf16* x = (const bf16*)d_in[0];
    const bf16* wr = (const bf16*)d_in[1];
    const bf16* wi = (const bf16*)d_in[2];
    const bf16* Bre = (const bf16*)d_in[6];
    const bf16* Bim = (const bf16*)d_in[7];
    const bf16* Cre = (const bf16*)d_in[8];
    const bf16* Cim = (const bf16*)d_in[9];

    void* fn = nullptr;
    cudaDriverEntryPointQueryResult st;
    cudaGetDriverEntryPoint("cuTensorMapEncodeTiled", &fn, cudaEnableDefault, &st);
    PFN_encodeTiled enc = (PFN_encodeTiled)fn;
    void *p_hT, *p_U;
    cudaGetSymbolAddress(&p_hT, g_hT);
    cudaGetSymbolAddress(&p_U, g_U);

    Params P;
    P.lam_re = (const bf16*)d_in[4]; P.lam_im = (const bf16*)d_in[5]; P.log_dt = (const bf16*)d_in[10];
    P.dskip = (const bf16*)d_in[11]; P.gate_w = (const bf16*)d_in[12]; P.c_re = Cre; P.c_im = Cim; P.w_r = wr; P.w_i = wi;
    P.swapB = Bim < Bre;

    for (int c = 0; c < 68; c++) P.perm[c] = c < 4 ? 32 + 8 * c : c < 36 ? ((c - 4) & 24) + ((c - 5) & 7) : c < 64 ? 32 + (c - 36) / 7 * 8 + ((c - 37 + 7) % 7 + 1) : c;

    CUtensorMap mB, mX, mCre, mCim, mXs, mU0, mV, mU2, mXe, mO, mH, mWr, mWi;
    {
        cuuint64_t d[3] = {64, 2052, 8}, s[2] = {128, 262656};
        cuuint32_t bx[3] = {64, 9, 8};
        mWr = make_map(enc, wr, 3, d, s, bx, CU_TENSOR_MAP_SWIZZLE_NONE);
        mWi = make_map(enc, wi, 3, d, s, bx, CU_TENSOR_MAP_SWIZZLE_NONE);
    }
    {
        cuuint64_t d[3] = {256, 16, 256}, s[2] = {2048, 32768};
        cuuint32_t bx[3] = {256, 1, 2};
        mH = make_map(enc, p_hT, 3, d, s, bx, CU_TENSOR_MAP_SWIZZLE_NONE, CU_TENSOR_MAP_DATA_TYPE_UINT64);
    }
    {
        const bf16* lo = P.swapB ? Bim : Bre; const bf16* hi = P.swapB ? Bre : Bim;
        cuuint64_t d[4] = {1024, 8, 2, 128}, s[3] = {2048, (cuuint64_t)((const char*)hi - (const char*)lo), 16384};
        cuuint32_t bx[4] = {64, 8, 2, 8};
        mB = make_map(enc, lo, 4, d, s, bx);
    }
    {
        cuuint64_t d[4] = {1024, 2, 4, 928}, s[3] = {2048, 64 * 2048, 2 * 2048};
        cuuint32_t bx[4] = {64, 2, 4, 32};
        mX = make_map(enc, x, 4, d, s, bx);
    }
    {
        cuuint64_t d[3] = {64, 1024, 16}, s[2] = {2048, 128};
        cuuint32_t bx[3] = {64, 128, 1};
        mCre = make_map(enc, Cre, 3, d, s, bx);
        mCim = make_map(enc, Cim, 3, d, s, bx);
    }
    {
        cuuint64_t d[3] = {64, 256, 128}, s[2] = {16384, 128};
        cuuint32_t bx[3] = {64, 64, 2};
        mV = make_map(enc, p_U, 3, d, s, bx);
        mXe = make_map(enc, x, 3, d, s, bx);
    }
    {
        cuuint64_t d[5] = {8192, 2, 2, 2, 32}, s[4] = {16 * 4096, 32 * 4096, 8 * 4096, 64 * 4096};
        cuuint32_t bx[5] = {32, 2, 2, 2, 2};
        mO = make_map(enc, d_out, 5, d, s, bx, CU_TENSOR_MAP_SWIZZLE_128B, CU_TENSOR_MAP_DATA_TYPE_FLOAT32);
    }
    {
        cuuint64_t d[4] = {1024, 64, 4, 8}, s[3] = {32 * 2048, 8 * 2048, 2048};
        cuuint32_t bx[4] = {32, 64, 4, 1};
        mXs = make_map(enc, x, 4, d, s, bx, CU_TENSOR_MAP_SWIZZLE_64B);
    }
    {
        cuuint64_t d[4] = {1024, 128, 2, 8}, s[3] = {32768, 16384, 2048};
        cuuint32_t bx[4] = {32, 128, 2, 1};
        mU0 = make_map(enc, p_U, 4, d, s, bx, CU_TENSOR_MAP_SWIZZLE_64B);
    }
    {
        cuuint64_t d[4] = {64, 8, 16, 256}, s[3] = {2048, 128, 16384};
        cuuint32_t bx[4] = {64, 8, 4, 1};
        mU2 = make_map(enc, p_U, 4, d, s, bx);
    }
    cudaFuncSetAttribute(fused_kernel, cudaFuncAttributeMaxDynamicSharedMemorySize, SMEM_BYTES);
    fused_kernel<<<130, 384, SMEM_BYTES, cudaStreamPerThread>>>(mB, mX, mXs, mU0, mU2, mXe, mCre, mCim, mV, mO, mH, mWr, mWi, P);
}
```

```cpp
#include <cuda_runtime.h>
#include <cuda_bf16.h>
#include <cuda.h>
#include <stdint.h>

typedef __nv_bfloat16 bf16;

__device__ const __align__(128) uint32_t c_tab[11264] = {
0x3f803f80,0xbf803f80,0x3f803f80,0xbf803f80,0x3f803f80,0xbf803f80,0x3f803f80,0xbf803f80,0x3f803f80,0xbf803f80,0x3f803f80,0xbf803f80,
0x3f803f80,0xbf803f80,0x3f803f80,0xbf803f80,0x3f7f3f80,0xbdc98000,0x3f223f35,0xbf46bf35,0x3f753f7b,0xbe95be48,0x3ef13f0e,0xbf62bf55,
0x3f623f6d,0xbef1bec4,0x3e953ec4,0xbf75bf6d,0x3f463f55,0xbf22bf0e,0x3dc93e48,0xbf7fbf7b,0x3f7b3f80,0xbe488000,0xbe480000,0xbf7bbf80,
0x3f553f6d,0xbf0ebec4,0xbf0ebec4,0xbf55bf6d,0x3f0e3f35,0xbf55bf35,0xbf55bf35,0xbf0ebf35,0x3e483ec4,0xbf7bbf6d,0xbf7bbf6d,0xbe48bec4,
0x3f753f80,0xbe958000,0xbf62bf35,0xbef1bf35,0x3f223f55,0xbf46bf0e,0xbf7fbf7b,0x3dc9be48,0x3dc93ec4,0xbf7fbf6d,0xbf46bf6d,0x3f223ec4,
0xbef1be48,0xbf62bf7b,0xbe95bf0e,0x3f753f55,0x3f6d3f80,0xbec48000,0xbf6dbf80,0x3ec48000,0x3ec43f35,0xbf6dbf35,0xbec4bf35,0x3f6d3f35,
0xbec40000,0xbf6dbf80,0x3ec40000,0x3f6d3f80,0xbf6dbf35,0xbec4bf35,0x3f6d3f35,0x3ec43f35,0x3f623f80,0xbef18000,0xbe95bf35,0x3f753f35,
0x3dc93f0e,0xbf7fbf55,0x3f223e48,0x3f463f7b,0xbf46bec4,0xbf22bf6d,0x3f7f3f6d,0xbdc93ec4,0xbf75bf7b,0x3e95be48,0x3ef13f55,0xbf62bf0e,
0x3f553f80,0xbf0e8000,0x3f0e0000,0x3f553f80,0xbe483ec4,0xbf7bbf6d,0x3f7b3f6d,0xbe483ec4,0xbf7bbf35,0xbe48bf35,0x3e483f35,0xbf7bbf35,
0xbf0ebf6d,0x3f553ec4,0xbf55bec4,0xbf0ebf6d,0x3f463f80,0xbf228000,0x3f7f3f35,0x3dc93f35,0xbef13e48,0xbf62bf7b,0x3e953f55,0xbf75bf0e,
0xbf75bf6d,0x3e95bec4,0xbf62bec4,0xbef1bf6d,0x3dc9bf0e,0x3f7f3f55,0xbf22bf7b,0x3f463e48,0x3f353f80,0xbf358000,0x3f353f80,0xbf358000,
0xbf350000,0xbf35bf80,0xbf350000,0xbf35bf80,0xbf35bf80,0x3f358000,0xbf35bf80,0x3f358000,0x3f350000,0x3f353f80,0x3f350000,0x3f353f80,
0x3f223f80,0xbf468000,0xbdc93f35,0xbf7fbf35,0xbf62be48,0xbef1bf7b,0xbf75bf55,0x3e95bf0e,0xbe95bf6d,0x3f753ec4,0x3ef1bec4,0x3f623f6d,
0x3f7f3f0e,0x3dc93f55,0x3f463f7b,0xbf223e48,0x3f0e3f80,0xbf558000,0xbf550000,0xbf0ebf80,0xbf7bbec4,0xbe48bf6d,0xbe48bf6d,0x3f7b3ec4,
0x3e48bf35,0x3f7b3f35,0x3f7b3f35,0xbe483f35,0x3f553f6d,0xbf0e3ec4,0xbf0e3ec4,0xbf55bf6d,0x3ef13f80,0xbf628000,0xbf75bf35,0x3e95bf35,
0xbf7fbf0e,0x3dc9bf55,0x3f46be48,0x3f223f7b,0x3f22bec4,0x3f463f6d,0x3dc93f6d,0xbf7fbec4,0x3e953f7b,0xbf75be48,0xbf62bf55,0x3ef1bf0e,
0x3ec43f80,0xbf6d8000,0xbec4bf80,0x3f6d8000,0xbf6dbf35,0x3ec4bf35,0x3f6d3f35,0xbec43f35,0x3f6d0000,0x3ec43f80,0xbf6d0000,0xbec4bf80,
0xbec43f35,0xbf6dbf35,0x3ec4bf35,0x3f6d3f35,0x3e953f80,0xbf758000,0x3ef1bf35,0x3f623f35,0xbf46bf55,0x3f22bf0e,0x3dc93f7b,0xbf7fbe48,
0x3f7f3ec4,0xbdc93f6d,0xbf22bf6d,0x3f46bec4,0xbf623e48,0xbef1bf7b,0x3f753f0e,0xbe953f55,0x3e483f80,0xbf7b8000,0x3f7b0000,0x3e483f80,
0xbf0ebf6d,0x3f55bec4,0xbf553ec4,0xbf0ebf6d,0x3f553f35,0xbf0e3f35,0x3f0ebf35,0x3f553f35,0xbf7bbec4,0x3e48bf6d,0xbe483f6d,0xbf7bbec4,
0x3dc93f80,0xbf7f8000,0x3f463f35,0xbf223f35,0xbe95bf7b,0x3f75be48,0xbf62bf0e,0x3ef1bf55,0x3ef13f6d,0xbf623ec4,0x3f753ec4,0xbe953f6d,
0xbf22bf55,0x3f46bf0e,0xbf7fbe48,0x3dc9bf7b,0x3f80,0xbf808000,0x3f80,0xbf808000,0xbf80,0x3f808000,0xbf80,0x3f808000,
0x3f80,0xbf808000,0x3f80,0xbf808000,0xbf80,0x3f808000,0xbf80,0x3f808000,0xbdc93f80,0xbf7f8000,0xbf463f35,0xbf22bf35,
0x3e95bf7b,0x3f753e48,0x3f62bf0e,0x3ef13f55,0xbef13f6d,0xbf62bec4,0xbf753ec4,0xbe95bf6d,0x3f22bf55,0x3f463f0e,0x3f7fbe48,0x3dc93f7b,
0xbe483f80,0xbf7b8000,0xbf7b0000,0x3e48bf80,0x3f0ebf6d,0x3f553ec4,0x3f553ec4,0xbf0e3f6d,0xbf553f35,0xbf0ebf35,0xbf0ebf35,0x3f55bf35,
0x3f7bbec4,0x3e483f6d,0x3e483f6d,0xbf7b3ec4,0xbe953f80,0xbf758000,0xbef1bf35,0x3f62bf35,0x3f46bf55,0x3f223f0e,0xbdc93f7b,0xbf7f3e48,
0xbf7f3ec4,0xbdc9bf6d,0x3f22bf6d,0x3f463ec4,0x3f623e48,0xbef13f7b,0xbf753f0e,0xbe95bf55,0xbec43f80,0xbf6d8000,0x3ec4bf80,0x3f6d8000,
0x3f6dbf35,0x3ec43f35,0xbf6d3f35,0xbec4bf35,0xbf6d0000,0x3ec4bf80,0x3f6d0000,0xbec43f80,0x3ec43f35,0xbf6d3f35,0xbec4bf35,0x3f6dbf35,
0xbef13f80,0xbf628000,0x3f75bf35,0x3e953f35,0x3f7fbf0e,0x3dc93f55,0xbf46be48,0x3f22bf7b,0xbf22bec4,0x3f46bf6d,0xbdc93f6d,0xbf7f3ec4,
0xbe953f7b,0xbf753e48,0x3f62bf55,0x3ef13f0e,0xbf0e3f80,0xbf558000,0x3f550000,0xbf0e3f80,0x3f7bbec4,0xbe483f6d,0x3e48bf6d,0x3f7bbec4,
0xbe48bf35,0x3f7bbf35,0xbf7b3f35,0xbe48bf35,0xbf553f6d,0xbf0ebec4,0x3f0e3ec4,0xbf553f6d,0xbf223f80,0xbf468000,0x3dc93f35,0xbf7f3f35,
0x3f62be48,0xbef13f7b,0x3f75bf55,0x3e953f0e,0x3e95bf6d,0x3f75bec4,0xbef1bec4,0x3f62bf6d,0xbf7f3f0e,0x3dc9bf55,0xbf463f7b,0xbf22be48,
0xbf353f80,0xbf358000,0xbf353f80,0xbf358000,0x3f350000,0xbf353f80,0x3f350000,0xbf353f80,0x3f35bf80,0x3f358000,0x3f35bf80,0x3f358000,
0xbf350000,0x3f35bf80,0xbf350000,0x3f35bf80,0xbf463f80,0xbf228000,0xbf7f3f35,0x3dc9bf35,0x3ef13e48,0xbf623f7b,0xbe953f55,0xbf753f0e,
0x3f75bf6d,0x3e953ec4,0x3f62bec4,0xbef13f6d,0xbdc9bf0e,0x3f7fbf55,0x3f22bf7b,0x3f46be48,0xbf553f80,0xbf0e8000,0xbf0e0000,0x3f55bf80,
0x3e483ec4,0xbf7b3f6d,0xbf7b3f6d,0xbe48bec4,0x3f7bbf35,0xbe483f35,0xbe483f35,0xbf7b3f35,0x3f0ebf6d,0x3f55bec4,0x3f55bec4,0xbf0e3f6d,
0xbf623f80,0xbef18000,0x3e95bf35,0x3f75bf35,0xbdc93f0e,0xbf7f3f55,0xbf223e48,0x3f46bf7b,0x3f46bec4,0xbf223f6d,0xbf7f3f6d,0xbdc9bec4,
0x3f75bf7b,0x3e953e48,0xbef13f55,0xbf623f0e,0xbf6d3f80,0xbec48000,0x3f6dbf80,0x3ec48000,0xbec43f35,0xbf6d3f35,0x3ec4bf35,0x3f6dbf35,
0x3ec40000,0xbf6d3f80,0xbec40000,0x3f6dbf80,0x3f6dbf35,0xbec43f35,0xbf6d3f35,0x3ec4bf35,0xbf753f80,0xbe958000,0x3f62bf35,0xbef13f35,
0xbf223f55,0xbf463f0e,0x3f7fbf7b,0x3dc93e48,0xbdc93ec4,0xbf7f3f6d,0x3f46bf6d,0x3f22bec4,0x3ef1be48,0xbf623f7b,0x3e95bf0e,0x3f75bf55,
0xbf7b3f80,0xbe488000,0x3e480000,0xbf7b3f80,0xbf553f6d,0xbf0e3ec4,0x3f0ebec4,0xbf553f6d,0xbf0e3f35,0xbf553f35,0x3f55bf35,0xbf0e3f35,
0xbe483ec4,0xbf7b3f6d,0x3f7bbf6d,0xbe483ec4,0xbf7f3f80,0xbdc98000,0xbf223f35,0xbf463f35,0xbf753f7b,0xbe953e48,0xbef13f0e,0xbf623f55,
0xbf623f6d,0xbef13ec4,0xbe953ec4,0xbf753f6d,0xbf463f55,0xbf223f0e,0xbdc93e48,0xbf7f3f7b,0x3f803f80,0xbf803f80,0x3f803f80,0xbf803f80,
0x3f803f80,0xbf803f80,0x3f803f80,0xbf803f80,0x3f803f80,0xbf803f80,0x3f803f80,0xbf803f80,0x3f803f80,0xbf803f80,0x3f803f80,0xbf803f80,
0xbdc90000,0xbf7fbf80,0xbf46bf35,0xbf22bf35,0xbe95be48,0xbf75bf7b,0xbf62bf55,0xbef1bf0e,0xbef1bec4,0xbf62bf6d,0xbf75bf6d,0xbe95bec4,
0xbf22bf0e,0xbf46bf55,0xbf7fbf7b,0xbdc9be48,0xbf7bbf80,0x3e488000,0x3e480000,0x3f7b3f80,0xbf55bf6d,0x3f0e3ec4,0x3f0e3ec4,0x3f553f6d,
0xbf0ebf35,0x3f553f35,0x3f553f35,0x3f0e3f35,0xbe48bec4,0x3f7b3f6d,0x3f7b3f6d,0x3e483ec4,0x3e950000,0x3f753f80,0x3ef13f35,0xbf62bf35,
0x3f463f0e,0x3f223f55,0xbdc93e48,0xbf7fbf7b,0x3f7f3f6d,0x3dc93ec4,0xbf22bec4,0xbf46bf6d,0x3f623f7b,0xbef1be48,0xbf75bf55,0xbe95bf0e,
0x3f6d3f80,0xbec48000,0xbf6dbf80,0x3ec48000,0x3ec43f35,0xbf6dbf35,0xbec4bf35,0x3f6d3f35,0xbec40000,0xbf6dbf80,0x3ec40000,0x3f6d3f80,
0xbf6dbf35,0xbec4bf35,0x3f6d3f35,0x3ec43f35,0xbef10000,0xbf62bf80,0x3f753f35,0x3e953f35,0xbf7fbf55,0xbdc9bf0e,0x3f463f7b,0xbf22be48,
0xbf22bf6d,0x3f463ec4,0xbdc93ec4,0xbf7fbf6d,0x3e95be48,0x3f753f7b,0xbf62bf0e,0xbef1bf55,0xbf55bf80,0x3f0e8000,0xbf0e0000,0xbf55bf80,
0x3e48bec4,0x3f7b3f6d,0xbf7bbf6d,0x3e48bec4,0x3f7b3f35,0x3e483f35,0xbe48bf35,0x3f7b3f35,0x3f0e3f6d,0xbf55bec4,0x3f553ec4,0x3f0e3f6d,
0x3f220000,0x3f463f80,0xbdc9bf35,0x3f7f3f35,0x3f623f7b,0xbef13e48,0x3f753f0e,0x3e953f55,0xbe953ec4,0xbf75bf6d,0x3ef13f6d,0xbf62bec4,
0xbf7fbf55,0x3dc9bf0e,0xbf46be48,0xbf22bf7b,0x3f353f80,0xbf358000,0x3f353f80,0xbf358000,0xbf350000,0xbf35bf80,0xbf350000,0xbf35bf80,
0xbf35bf80,0x3f358000,0xbf35bf80,0x3f358000,0x3f350000,0x3f353f80,0x3f350000,0x3f353f80,0xbf460000,0xbf22bf80,0xbf7fbf35,0x3dc9bf35,
0xbef1bf7b,0x3f623e48,0x3e95bf0e,0x3f753f55,0x3f753ec4,0x3e953f6d,0x3f623f6d,0xbef13ec4,0x3dc93f55,0xbf7fbf0e,0xbf223e48,0xbf46bf7b,
0xbf0ebf80,0x3f558000,0x3f550000,0x3f0e3f80,0x3f7b3ec4,0x3e483f6d,0x3e483f6d,0xbf7bbec4,0xbe483f35,0xbf7bbf35,0xbf7bbf35,0x3e48bf35,
0xbf55bf6d,0x3f0ebec4,0x3f0ebec4,0x3f553f6d,0x3f620000,0x3ef13f80,0xbe953f35,0xbf75bf35,0xbdc93f55,0xbf7fbf0e,0xbf22bf7b,0x3f46be48,
0xbf46bf6d,0x3f22bec4,0x3f7f3ec4,0x3dc93f6d,0x3f753e48,0x3e953f7b,0xbef13f0e,0xbf62bf55,0x3ec43f80,0xbf6d8000,0xbec4bf80,0x3f6d8000,
0xbf6dbf35,0x3ec4bf35,0x3f6d3f35,0xbec43f35,0x3f6d0000,0x3ec43f80,0xbf6d0000,0xbec4bf80,0xbec43f35,0xbf6dbf35,0x3ec4bf35,0x3f6d3f35,
0xbf750000,0xbe95bf80,0x3f623f35,0xbef13f35,0x3f22bf0e,0x3f463f55,0xbf7fbe48,0xbdc9bf7b,0xbdc93f6d,0xbf7fbec4,0x3f46bec4,0x3f223f6d,
0xbef1bf7b,0x3f62be48,0xbe953f55,0xbf75bf0e,0xbe48bf80,0x3f7b8000,0xbf7b0000,0xbe48bf80,0x3f0e3f6d,0xbf553ec4,0x3f55bec4,0x3f0e3f6d,
0xbf55bf35,0x3f0ebf35,0xbf0e3f35,0xbf55bf35,0x3f7b3ec4,0xbe483f6d,0x3e48bf6d,0x3f7b3ec4,0x3f7f0000,0x3dc93f80,0x3f22bf35,0x3f463f35,
0xbf753e48,0xbe95bf7b,0xbef13f55,0xbf62bf0e,0x3f62bec4,0x3ef13f6d,0x3e95bf6d,0x3f753ec4,0xbf463f0e,0xbf22bf55,0xbdc93f7b,0xbf7fbe48,
0x3f80,0xbf808000,0x3f80,0xbf808000,0xbf80,0x3f808000,0xbf80,0x3f808000,0x3f80,0xbf808000,0x3f80,0xbf808000,
0xbf80,0x3f808000,0xbf80,0x3f808000,0xbf7f0000,0x3dc9bf80,0xbf22bf35,0x3f46bf35,0x3f753e48,0xbe953f7b,0x3ef13f55,0xbf623f0e,
0xbf62bec4,0x3ef1bf6d,0xbe95bf6d,0x3f75bec4,0x3f463f0e,0xbf223f55,0x3dc93f7b,0xbf7f3e48,0x3e48bf80,0x3f7b8000,0x3f7b0000,0xbe483f80,
0xbf0e3f6d,0xbf55bec4,0xbf55bec4,0x3f0ebf6d,0x3f55bf35,0x3f0e3f35,0x3f0e3f35,0xbf553f35,0xbf7b3ec4,0xbe48bf6d,0xbe48bf6d,0x3f7bbec4,
0x3f750000,0xbe953f80,0xbf623f35,0xbef1bf35,0xbf22bf0e,0x3f46bf55,0x3f7fbe48,0xbdc93f7b,0x3dc93f6d,0xbf7f3ec4,0xbf46bec4,0x3f22bf6d,
0x3ef1bf7b,0x3f623e48,0x3e953f55,0xbf753f0e,0xbec43f80,0xbf6d8000,0x3ec4bf80,0x3f6d8000,0x3f6dbf35,0x3ec43f35,0xbf6d3f35,0xbec4bf35,
0xbf6d0000,0x3ec4bf80,0x3f6d0000,0xbec43f80,0x3ec43f35,0xbf6d3f35,0xbec4bf35,0x3f6dbf35,0xbf620000,0x3ef1bf80,0x3e953f35,0xbf753f35,
0x3dc93f55,0xbf7f3f0e,0x3f22bf7b,0x3f463e48,0x3f46bf6d,0x3f223ec4,0xbf7f3ec4,0x3dc9bf6d,0xbf753e48,0x3e95bf7b,0x3ef13f0e,0xbf623f55,
0x3f0ebf80,0x3f558000,0xbf550000,0x3f0ebf80,0xbf7b3ec4,0x3e48bf6d,0xbe483f6d,0xbf7b3ec4,0x3e483f35,0xbf7b3f35,0x3f7bbf35,0x3e483f35,
0x3f55bf6d,0x3f0e3ec4,0xbf0ebec4,0x3f55bf6d,0x3f460000,0xbf223f80,0x3f7fbf35,0x3dc93f35,0x3ef1bf7b,0x3f62be48,0xbe95bf0e,0x3f75bf55,
0xbf753ec4,0x3e95bf6d,0xbf623f6d,0xbef1bec4,0xbdc93f55,0xbf7f3f0e,0x3f223e48,0xbf463f7b,0xbf353f80,0xbf358000,0xbf353f80,0xbf358000,
0x3f350000,0xbf353f80,0x3f350000,0xbf353f80,0x3f35bf80,0x3f358000,0x3f35bf80,0x3f358000,0xbf350000,0x3f35bf80,0xbf350000,0x3f35bf80,
0xbf220000,0x3f46bf80,0x3dc9bf35,0x3f7fbf35,0xbf623f7b,0xbef1be48,0xbf753f0e,0x3e95bf55,0x3e953ec4,0xbf753f6d,0xbef13f6d,0xbf623ec4,
0x3f7fbf55,0x3dc93f0e,0x3f46be48,0xbf223f7b,0x3f55bf80,0x3f0e8000,0x3f0e0000,0xbf553f80,0xbe48bec4,0x3f7bbf6d,0x3f7bbf6d,0x3e483ec4,
0xbf7b3f35,0x3e48bf35,0x3e48bf35,0x3f7bbf35,0xbf0e3f6d,0xbf553ec4,0xbf553ec4,0x3f0ebf6d,0x3ef10000,0xbf623f80,0xbf753f35,0x3e95bf35,
0x3f7fbf55,0xbdc93f0e,0xbf463f7b,0xbf223e48,0x3f22bf6d,0x3f46bec4,0x3dc93ec4,0xbf7f3f6d,0xbe95be48,0x3f75bf7b,0x3f62bf0e,0xbef13f55,
0xbf6d3f80,0xbec48000,0x3f6dbf80,0x3ec48000,0xbec43f35,0xbf6d3f35,0x3ec4bf35,0x3f6dbf35,0x3ec40000,0xbf6d3f80,0xbec40000,0x3f6dbf80,
0x3f6dbf35,0xbec43f35,0xbf6d3f35,0x3ec4bf35,0xbe950000,0x3f75bf80,0xbef13f35,0xbf623f35,0xbf463f0e,0x3f22bf55,0x3dc93e48,0xbf7f3f7b,
0xbf7f3f6d,0x3dc9bec4,0x3f22bec4,0xbf463f6d,0xbf623f7b,0xbef13e48,0x3f75bf55,0xbe953f0e,0x3f7bbf80,0x3e488000,0xbe480000,0x3f7bbf80,
0x3f55bf6d,0x3f0ebec4,0xbf0e3ec4,0x3f55bf6d,0x3f0ebf35,0x3f55bf35,0xbf553f35,0x3f0ebf35,0x3e48bec4,0x3f7bbf6d,0xbf7b3f6d,0x3e48bec4,
0x3dc90000,0xbf7f3f80,0x3f46bf35,0xbf223f35,0x3e95be48,0xbf753f7b,0x3f62bf55,0xbef13f0e,0x3ef1bec4,0xbf623f6d,0x3f75bf6d,0xbe953ec4,
0x3f22bf0e,0xbf463f55,0x3f7fbf7b,0xbdc93e48,0x3f803f80,0xbf803f80,0x3f803f80,0xbf803f80,0x3f803f80,0xbf803f80,0x3f803f80,0xbf803f80,
0x3f803f80,0xbf803f80,0x3f803f80,0xbf803f80,0x3f803f80,0xbf803f80,0x3f803f80,0xbf803f80,0xbf7fbf80,0x3dc98000,0xbf22bf35,0x3f463f35,
0xbf75bf7b,0x3e953e48,0xbef1bf0e,0x3f623f55,0xbf62bf6d,0x3ef13ec4,0xbe95bec4,0x3f753f6d,0xbf46bf55,0x3f223f0e,0xbdc9be48,0x3f7f3f7b,
0x3f7b3f80,0xbe488000,0xbe480000,0xbf7bbf80,0x3f553f6d,0xbf0ebec4,0xbf0ebec4,0xbf55bf6d,0x3f0e3f35,0xbf55bf35,0xbf55bf35,0xbf0ebf35,
0x3e483ec4,0xbf7bbf6d,0xbf7bbf6d,0xbe48bec4,0xbf75bf80,0x3e958000,0x3f623f35,0x3ef13f35,0xbf22bf55,0x3f463f0e,0x3f7f3f7b,0xbdc93e48,
0xbdc9bec4,0x3f7f3f6d,0x3f463f6d,0xbf22bec4,0x3ef13e48,0x3f623f7b,0x3e953f0e,0xbf75bf55,0x3f6d3f80,0xbec48000,0xbf6dbf80,0x3ec48000,
0x3ec43f35,0xbf6dbf35,0xbec4bf35,0x3f6d3f35,0xbec40000,0xbf6dbf80,0x3ec40000,0x3f6d3f80,0xbf6dbf35,0xbec4bf35,0x3f6d3f35,0x3ec43f35,
0xbf62bf80,0x3ef18000,0x3e953f35,0xbf75bf35,0xbdc9bf0e,0x3f7f3f55,0xbf22be48,0xbf46bf7b,0x3f463ec4,0x3f223f6d,0xbf7fbf6d,0x3dc9bec4,
0x3f753f7b,0xbe953e48,0xbef1bf55,0x3f623f0e,0x3f553f80,0xbf0e8000,0x3f0e0000,0x3f553f80,0xbe483ec4,0xbf7bbf6d,0x3f7b3f6d,0xbe483ec4,
0xbf7bbf35,0xbe48bf35,0x3e483f35,0xbf7bbf35,0xbf0ebf6d,0x3f553ec4,0xbf55bec4,0xbf0ebf6d,0xbf46bf80,0x3f228000,0xbf7fbf35,0xbdc9bf35,
0x3ef1be48,0x3f623f7b,0xbe95bf55,0x3f753f0e,0x3f753f6d,0xbe953ec4,0x3f623ec4,0x3ef13f6d,0xbdc93f0e,0xbf7fbf55,0x3f223f7b,0xbf46be48,
0x3f353f80,0xbf358000,0x3f353f80,0xbf358000,0xbf350000,0xbf35bf80,0xbf350000,0xbf35bf80,0xbf35bf80,0x3f358000,0xbf35bf80,0x3f358000,
0x3f350000,0x3f353f80,0x3f350000,0x3f353f80,0xbf22bf80,0x3f468000,0x3dc9bf35,0x3f7f3f35,0x3f623e48,0x3ef13f7b,0x3f753f55,0xbe953f0e,
0x3e953f6d,0xbf75bec4,0xbef13ec4,0xbf62bf6d,0xbf7fbf0e,0xbdc9bf55,0xbf46bf7b,0x3f22be48,0x3f0e3f80,0xbf558000,0xbf550000,0xbf0ebf80,
0xbf7bbec4,0xbe48bf6d,0xbe48bf6d,0x3f7b3ec4,0x3e48bf35,0x3f7b3f35,0x3f7b3f35,0xbe483f35,0x3f553f6d,0xbf0e3ec4,0xbf0e3ec4,0xbf55bf6d,
0xbef1bf80,0x3f628000,0x3f753f35,0xbe953f35,0x3f7f3f0e,0xbdc93f55,0xbf463e48,0xbf22bf7b,0xbf223ec4,0xbf46bf6d,0xbdc9bf6d,0x3f7f3ec4,
0xbe95bf7b,0x3f753e48,0x3f623f55,0xbef13f0e,0x3ec43f80,0xbf6d8000,0xbec4bf80,0x3f6d8000,0xbf6dbf35,0x3ec4bf35,0x3f6d3f35,0xbec43f35,
0x3f6d0000,0x3ec43f80,0xbf6d0000,0xbec4bf80,0xbec43f35,0xbf6dbf35,0x3ec4bf35,0x3f6d3f35,0xbe95bf80,0x3f758000,0xbef13f35,0xbf62bf35,
0x3f463f55,0xbf223f0e,0xbdc9bf7b,0x3f7f3e48,0xbf7fbec4,0x3dc9bf6d,0x3f223f6d,0xbf463ec4,0x3f62be48,0x3ef13f7b,0xbf75bf0e,0x3e95bf55,
0x3e483f80,0xbf7b8000,0x3f7b0000,0x3e483f80,0xbf0ebf6d,0x3f55bec4,0xbf553ec4,0xbf0ebf6d,0x3f553f35,0xbf0e3f35,0x3f0ebf35,0x3f553f35,
0xbf7bbec4,0x3e48bf6d,0xbe483f6d,0xbf7bbec4,0xbdc9bf80,0x3f7f8000,0xbf46bf35,0x3f22bf35,0x3e953f7b,0xbf753e48,0x3f623f0e,0xbef13f55,
0xbef1bf6d,0x3f62bec4,0xbf75bec4,0x3e95bf6d,0x3f223f55,0xbf463f0e,0x3f7f3e48,0xbdc93f7b,0x3f80,0xbf808000,0x3f80,0xbf808000,
0xbf80,0x3f808000,0xbf80,0x3f808000,0x3f80,0xbf808000,0x3f80,0xbf808000,0xbf80,0x3f808000,0xbf80,0x3f808000,
0x3dc9bf80,0x3f7f8000,0x3f46bf35,0x3f223f35,0xbe953f7b,0xbf75be48,0xbf623f0e,0xbef1bf55,0x3ef1bf6d,0x3f623ec4,0x3f75bec4,0x3e953f6d,
0xbf223f55,0xbf46bf0e,0xbf7f3e48,0xbdc9bf7b,0xbe483f80,0xbf7b8000,0xbf7b0000,0x3e48bf80,0x3f0ebf6d,0x3f553ec4,0x3f553ec4,0xbf0e3f6d,
0xbf553f35,0xbf0ebf35,0xbf0ebf35,0x3f55bf35,0x3f7bbec4,0x3e483f6d,0x3e483f6d,0xbf7b3ec4,0x3e95bf80,0x3f758000,0x3ef13f35,0xbf623f35,
0xbf463f55,0xbf22bf0e,0x3dc9bf7b,0x3f7fbe48,0x3f7fbec4,0x3dc93f6d,0xbf223f6d,0xbf46bec4,0xbf62be48,0x3ef1bf7b,0x3f75bf0e,0x3e953f55,
0xbec43f80,0xbf6d8000,0x3ec4bf80,0x3f6d8000,0x3f6dbf35,0x3ec43f35,0xbf6d3f35,0xbec4bf35,0xbf6d0000,0x3ec4bf80,0x3f6d0000,0xbec43f80,
0x3ec43f35,0xbf6d3f35,0xbec4bf35,0x3f6dbf35,0x3ef1bf80,0x3f628000,0xbf753f35,0xbe95bf35,0xbf7f3f0e,0xbdc9bf55,0x3f463e48,0xbf223f7b,
0x3f223ec4,0xbf463f6d,0x3dc9bf6d,0x3f7fbec4,0x3e95bf7b,0x3f75be48,0xbf623f55,0xbef1bf0e,0xbf0e3f80,0xbf558000,0x3f550000,0xbf0e3f80,
0x3f7bbec4,0xbe483f6d,0x3e48bf6d,0x3f7bbec4,0xbe48bf35,0x3f7bbf35,0xbf7b3f35,0xbe48bf35,0xbf553f6d,0xbf0ebec4,0x3f0e3ec4,0xbf553f6d,
0x3f22bf80,0x3f468000,0xbdc9bf35,0x3f7fbf35,0xbf623e48,0x3ef1bf7b,0xbf753f55,0xbe95bf0e,0xbe953f6d,0xbf753ec4,0x3ef13ec4,0xbf623f6d,
0x3f7fbf0e,0xbdc93f55,0x3f46bf7b,0x3f223e48,0xbf353f80,0xbf358000,0xbf353f80,0xbf358000,0x3f350000,0xbf353f80,0x3f350000,0xbf353f80,
0x3f35bf80,0x3f358000,0x3f35bf80,0x3f358000,0xbf350000,0x3f35bf80,0xbf350000,0x3f35bf80,0x3f46bf80,0x3f228000,0x3f7fbf35,0xbdc93f35,
0xbef1be48,0x3f62bf7b,0x3e95bf55,0x3f75bf0e,0xbf753f6d,0xbe95bec4,0xbf623ec4,0x3ef1bf6d,0x3dc93f0e,0xbf7f3f55,0xbf223f7b,0xbf463e48,
0xbf553f80,0xbf0e8000,0xbf0e0000,0x3f55bf80,0x3e483ec4,0xbf7b3f6d,0xbf7b3f6d,0xbe48bec4,0x3f7bbf35,0xbe483f35,0xbe483f35,0xbf7b3f35,
0x3f0ebf6d,0x3f55bec4,0x3f55bec4,0xbf0e3f6d,0x3f62bf80,0x3ef18000,0xbe953f35,0xbf753f35,0x3dc9bf0e,0x3f7fbf55,0x3f22be48,0xbf463f7b,
0xbf463ec4,0x3f22bf6d,0x3f7fbf6d,0x3dc93ec4,0xbf753f7b,0xbe95be48,0x3ef1bf55,0x3f62bf0e,0xbf6d3f80,0xbec48000,0x3f6dbf80,0x3ec48000,
0xbec43f35,0xbf6d3f35,0x3ec4bf35,0x3f6dbf35,0x3ec40000,0xbf6d3f80,0xbec40000,0x3f6dbf80,0x3f6dbf35,0xbec43f35,0xbf6d3f35,0x3ec4bf35,
0x3f75bf80,0x3e958000,0xbf623f35,0x3ef1bf35,0x3f22bf55,0x3f46bf0e,0xbf7f3f7b,0xbdc9be48,0x3dc9bec4,0x3f7fbf6d,0xbf463f6d,0xbf223ec4,
0xbef13e48,0x3f62bf7b,0xbe953f0e,0xbf753f55,0xbf7b3f80,0xbe488000,0x3e480000,0xbf7b3f80,0xbf553f6d,0xbf0e3ec4,0x3f0ebec4,0xbf553f6d,
0xbf0e3f35,0xbf553f35,0x3f55bf35,0xbf0e3f35,0xbe483ec4,0xbf7b3f6d,0x3f7bbf6d,0xbe483ec4,0x3f7fbf80,0x3dc98000,0x3f22bf35,0x3f46bf35,
0x3f75bf7b,0x3e95be48,0x3ef1bf0e,0x3f62bf55,0x3f62bf6d,0x3ef1bec4,0x3e95bec4,0x3f75bf6d,0x3f46bf55,0x3f22bf0e,0x3dc9be48,0x3f7fbf7b,
0x3f803f80,0xbf803f80,0x3f803f80,0xbf803f80,0x3f803f80,0xbf803f80,0x3f803f80,0xbf803f80,0x3f803f80,0xbf803f80,0x3f803f80,0xbf803f80,
0x3f803f80,0xbf803f80,0x3f803f80,0xbf803f80,0x3dc90000,0x3f7f3f80,0x3f463f35,0x3f223f35,0x3e953e48,0x3f753f7b,0x3f623f55,0x3ef13f0e,
0x3ef13ec4,0x3f623f6d,0x3f753f6d,0x3e953ec4,0x3f223f0e,0x3f463f55,0x3f7f3f7b,0x3dc93e48,0xbf7bbf80,0x3e488000,0x3e480000,0x3f7b3f80,
0xbf55bf6d,0x3f0e3ec4,0x3f0e3ec4,0x3f553f6d,0xbf0ebf35,0x3f553f35,0x3f553f35,0x3f0e3f35,0xbe48bec4,0x3f7b3f6d,0x3f7b3f6d,0x3e483ec4,
0xbe950000,0xbf75bf80,0xbef1bf35,0x3f623f35,0xbf46bf0e,0xbf22bf55,0x3dc9be48,0x3f7f3f7b,0xbf7fbf6d,0xbdc9bec4,0x3f223ec4,0x3f463f6d,
0xbf62bf7b,0x3ef13e48,0x3f753f55,0x3e953f0e,0x3f6d3f80,0xbec48000,0xbf6dbf80,0x3ec48000,0x3ec43f35,0xbf6dbf35,0xbec4bf35,0x3f6d3f35,
0xbec40000,0xbf6dbf80,0x3ec40000,0x3f6d3f80,0xbf6dbf35,0xbec4bf35,0x3f6d3f35,0x3ec43f35,0x3ef10000,0x3f623f80,0xbf75bf35,0xbe95bf35,
0x3f7f3f55,0x3dc93f0e,0xbf46bf7b,0x3f223e48,0x3f223f6d,0xbf46bec4,0x3dc9bec4,0x3f7f3f6d,0xbe953e48,0xbf75bf7b,0x3f623f0e,0x3ef13f55,
0xbf55bf80,0x3f0e8000,0xbf0e0000,0xbf55bf80,0x3e48bec4,0x3f7b3f6d,0xbf7bbf6d,0x3e48bec4,0x3f7b3f35,0x3e483f35,0xbe48bf35,0x3f7b3f35,
0x3f0e3f6d,0xbf55bec4,0x3f553ec4,0x3f0e3f6d,0xbf220000,0xbf46bf80,0x3dc93f35,0xbf7fbf35,0xbf62bf7b,0x3ef1be48,0xbf75bf0e,0xbe95bf55,
0x3e95bec4,0x3f753f6d,0xbef1bf6d,0x3f623ec4,0x3f7f3f55,0xbdc93f0e,0x3f463e48,0x3f223f7b,0x3f353f80,0xbf358000,0x3f353f80,0xbf358000,
0xbf350000,0xbf35bf80,0xbf350000,0xbf35bf80,0xbf35bf80,0x3f358000,0xbf35bf80,0x3f358000,0x3f350000,0x3f353f80,0x3f350000,0x3f353f80,
0x3f460000,0x3f223f80,0x3f7f3f35,0xbdc93f35,0x3ef13f7b,0xbf62be48,0xbe953f0e,0xbf75bf55,0xbf75bec4,0xbe95bf6d,0xbf62bf6d,0x3ef1bec4,
0xbdc9bf55,0x3f7f3f0e,0x3f22be48,0x3f463f7b,0xbf0ebf80,0x3f558000,0x3f550000,0x3f0e3f80,0x3f7b3ec4,0x3e483f6d,0x3e483f6d,0xbf7bbec4,
0xbe483f35,0xbf7bbf35,0xbf7bbf35,0x3e48bf35,0xbf55bf6d,0x3f0ebec4,0x3f0ebec4,0x3f553f6d,0xbf620000,0xbef1bf80,0x3e95bf35,0x3f753f35,
0x3dc9bf55,0x3f7f3f0e,0x3f223f7b,0xbf463e48,0x3f463f6d,0xbf223ec4,0xbf7fbec4,0xbdc9bf6d,0xbf75be48,0xbe95bf7b,0x3ef1bf0e,0x3f623f55,
0x3ec43f80,0xbf6d8000,0xbec4bf80,0x3f6d8000,0xbf6dbf35,0x3ec4bf35,0x3f6d3f35,0xbec43f35,0x3f6d0000,0x3ec43f80,0xbf6d0000,0xbec4bf80,
0xbec43f35,0xbf6dbf35,0x3ec4bf35,0x3f6d3f35,0x3f750000,0x3e953f80,0xbf62bf35,0x3ef1bf35,0xbf223f0e,0xbf46bf55,0x3f7f3e48,0x3dc93f7b,
0x3dc9bf6d,0x3f7f3ec4,0xbf463ec4,0xbf22bf6d,0x3ef13f7b,0xbf623e48,0x3e95bf55,0x3f753f0e,0xbe48bf80,0x3f7b8000,0xbf7b0000,0xbe48bf80,
0x3f0e3f6d,0xbf553ec4,0x3f55bec4,0x3f0e3f6d,0xbf55bf35,0x3f0ebf35,0xbf0e3f35,0xbf55bf35,0x3f7b3ec4,0xbe483f6d,0x3e48bf6d,0x3f7b3ec4,
0xbf7f0000,0xbdc9bf80,0xbf223f35,0xbf46bf35,0x3f75be48,0x3e953f7b,0x3ef1bf55,0x3f623f0e,0xbf623ec4,0xbef1bf6d,0xbe953f6d,0xbf75bec4,
0x3f46bf0e,0x3f223f55,0x3dc9bf7b,0x3f7f3e48,0x3f80,0xbf808000,0x3f80,0xbf808000,0xbf80,0x3f808000,0xbf80,0x3f808000,
0x3f80,0xbf808000,0x3f80,0xbf808000,0xbf80,0x3f808000,0xbf80,0x3f808000,0x3f7f0000,0xbdc93f80,0x3f223f35,0xbf463f35,
0xbf75be48,0x3e95bf7b,0xbef1bf55,0x3f62bf0e,0x3f623ec4,0xbef13f6d,0x3e953f6d,0xbf753ec4,0xbf46bf0e,0x3f22bf55,0xbdc9bf7b,0x3f7fbe48,
0x3e48bf80,0x3f7b8000,0x3f7b0000,0xbe483f80,0xbf0e3f6d,0xbf55bec4,0xbf55bec4,0x3f0ebf6d,0x3f55bf35,0x3f0e3f35,0x3f0e3f35,0xbf553f35,
0xbf7b3ec4,0xbe48bf6d,0xbe48bf6d,0x3f7bbec4,0xbf750000,0x3e95bf80,0x3f62bf35,0x3ef13f35,0x3f223f0e,0xbf463f55,0xbf7f3e48,0x3dc9bf7b,
0xbdc9bf6d,0x3f7fbec4,0x3f463ec4,0xbf223f6d,0xbef13f7b,0xbf62be48,0xbe95bf55,0x3f75bf0e,0xbec43f80,0xbf6d8000,0x3ec4bf80,0x3f6d8000,
0x3f6dbf35,0x3ec43f35,0xbf6d3f35,0xbec4bf35,0xbf6d0000,0x3ec4bf80,0x3f6d0000,0xbec43f80,0x3ec43f35,0xbf6d3f35,0xbec4bf35,0x3f6dbf35,
0x3f620000,0xbef13f80,0xbe95bf35,0x3f75bf35,0xbdc9bf55,0x3f7fbf0e,0xbf223f7b,0xbf46be48,0xbf463f6d,0xbf22bec4,0x3f7fbec4,0xbdc93f6d,
0x3f75be48,0xbe953f7b,0xbef1bf0e,0x3f62bf55,0x3f0ebf80,0x3f558000,0xbf550000,0x3f0ebf80,0xbf7b3ec4,0x3e48bf6d,0xbe483f6d,0xbf7b3ec4,
0x3e483f35,0xbf7b3f35,0x3f7bbf35,0x3e483f35,0x3f55bf6d,0x3f0e3ec4,0xbf0ebec4,0x3f55bf6d,0xbf460000,0x3f22bf80,0xbf7f3f35,0xbdc9bf35,
0xbef13f7b,0xbf623e48,0x3e953f0e,0xbf753f55,0x3f75bec4,0xbe953f6d,0x3f62bf6d,0x3ef13ec4,0x3dc9bf55,0x3f7fbf0e,0xbf22be48,0x3f46bf7b,
0xbf353f80,0xbf358000,0xbf353f80,0xbf358000,0x3f350000,0xbf353f80,0x3f350000,0xbf353f80,0x3f35bf80,0x3f358000,0x3f35bf80,0x3f358000,
0xbf350000,0x3f35bf80,0xbf350000,0x3f35bf80,0x3f220000,0xbf463f80,0xbdc93f35,0xbf7f3f35,0x3f62bf7b,0x3ef13e48,0x3f75bf0e,0xbe953f55,
0xbe95bec4,0x3f75bf6d,0x3ef1bf6d,0x3f62bec4,0xbf7f3f55,0xbdc9bf0e,0xbf463e48,0x3f22bf7b,0x3f55bf80,0x3f0e8000,0x3f0e0000,0xbf553f80,
0xbe48bec4,0x3f7bbf6d,0x3f7bbf6d,0x3e483ec4,0xbf7b3f35,0x3e48bf35,0x3e48bf35,0x3f7bbf35,0xbf0e3f6d,0xbf553ec4,0xbf553ec4,0x3f0ebf6d,
0xbef10000,0x3f62bf80,0x3f75bf35,0xbe953f35,0xbf7f3f55,0x3dc9bf0e,0x3f46bf7b,0x3f22be48,0xbf223f6d,0xbf463ec4,0xbdc9bec4,0x3f7fbf6d,
0x3e953e48,0xbf753f7b,0xbf623f0e,0x3ef1bf55,0xbf6d3f80,0xbec48000,0x3f6dbf80,0x3ec48000,0xbec43f35,0xbf6d3f35,0x3ec4bf35,0x3f6dbf35,
0x3ec40000,0xbf6d3f80,0xbec40000,0x3f6dbf80,0x3f6dbf35,0xbec43f35,0xbf6d3f35,0x3ec4bf35,0x3e950000,0xbf753f80,0x3ef1bf35,0x3f62bf35,
0x3f46bf0e,0xbf223f55,0xbdc9be48,0x3f7fbf7b,0x3f7fbf6d,0xbdc93ec4,0xbf223ec4,0x3f46bf6d,0x3f62bf7b,0x3ef1be48,0xbf753f55,0x3e95bf0e,
0x3f7bbf80,0x3e488000,0xbe480000,0x3f7bbf80,0x3f55bf6d,0x3f0ebec4,0xbf0e3ec4,0x3f55bf6d,0x3f0ebf35,0x3f55bf35,0xbf553f35,0x3f0ebf35,
0x3e48bec4,0x3f7bbf6d,0xbf7b3f6d,0x3e48bec4,0xbdc90000,0x3f7fbf80,0xbf463f35,0x3f22bf35,0xbe953e48,0x3f75bf7b,0xbf623f55,0x3ef1bf0e,
0xbef13ec4,0x3f62bf6d,0xbf753f6d,0x3e95bec4,0xbf223f0e,0x3f46bf55,0xbf7f3f7b,0x3dc9be48,0x3f803f80,0xbf353f35,0x3f803f80,0xbf353f35,
0x3f803f80,0xbf353f35,0x3f803f80,0xbf353f35,0x3f803f80,0xbf353f35,0x3f803f80,0xbf353f35,0x3f803f80,0xbf353f35,0x3f803f80,0xbf353f35,
0x3f7e3f80,0xbdfbbcc9,0x3f1d3f31,0xbf4abf39,0x3f733f7a,0xbea1be60,0x3ee63f09,0xbf65bf58,0x3f5f3f6a,0xbefcbecf,0x3e893eb8,0xbf77bf6f,
0x3f423f51,0xbf27bf13,0x3d973e2f,0xbf7fbf7c,0x3f783f80,0xbe79bd49,0xbe79bd49,0xbf78bf80,0x3f4e3f67,0xbf18bedb,0xbf18bedb,0xbf4ebf67,
0x3f043f2c,0xbf5cbf3e,0xbf5cbf3e,0xbf04bf2c,0x3e163eac,0xbf7dbf71,0xbf7dbf71,0xbe16beac,0x3f6f3f7f,0xbeb8bd97,0xbf6abf42,0xbecfbf27,
0x3f133f4a,0xbf51bf1d,0xbf7cbf7e,0x3e2fbdfb,0x3cc93ea1,0xbf80bf73,0xbf39bf65,0x3f313ee6,0xbf09be89,0xbf58bf77,0xbe60befc,0x3f7a3f5f,
0x3f623f7f,0xbef1bdc9,0xbf62bf7f,0x3ef13dc9,0x3e953f22,0xbf75bf46,0xbe95bf22,0x3f753f46,0xbef1bdc9,0xbf62bf7f,0x3ef13dc9,0x3f623f7f,
0xbf75bf46,0xbe95bf22,0x3f753f46,0x3e953f22,0x3f513f7e,0xbf13bdfb,0xbe2fbf1d,0x3f7c3f4a,0xbcc93ee6,0xbf80bf65,0x3f393ea1,0x3f313f73,
0xbf58befc,0xbf09bf5f,0x3f7a3f77,0xbe603e89,0xbf6abf7f,0x3ecfbd97,0x3eb83f42,0xbf6fbf27,0x3f3e3f7d,0xbf2cbe16,0x3f2c3e16,0x3f3e3f7d,
0xbeac3e79,0xbf71bf78,0x3f713f78,0xbeac3e79,0xbf80bf4e,0xbd49bf18,0x3d493f18,0xbf80bf4e,0xbedbbf5c,0x3f673f04,0xbf67bf04,0xbedbbf5c,
0x3f273f7c,0xbf42be2f,0x3f7f3f51,0xbd973f13,0xbf1d3cc9,0xbf4abf80,0x3dfb3f39,0xbf7ebf31,0xbf65bf7a,0x3ee6be60,0xbf73bf09,0xbea1bf58,
0x3e89becf,0x3f773f6a,0xbefcbf6f,0x3f5f3eb8,0x3f0e3f7b,0xbf55be48,0x3f0e3f7b,0xbf55be48,0xbf55be48,0xbf0ebf7b,0xbf55be48,0xbf0ebf7b,
0xbf0ebf7b,0x3f553e48,0xbf0ebf7b,0x3f553e48,0x3f553e48,0x3f0e3f7b,0x3f553e48,0x3f0e3f7b,0x3ee63f7a,0xbf65be60,0xbea13f09,0xbf73bf58,
0xbf77becf,0xbe89bf6a,0xbf5fbf6f,0x3efcbeb8,0xbd97bf51,0x3f7f3f13,0x3f27be2f,0x3f423f7c,0x3f7e3f39,0xbdfb3f31,0x3f1d3f80,0xbf4abcc9,
0x3eac3f78,0xbf71be79,0xbf71be79,0xbeacbf78,0xbf80bf18,0x3d49bf4e,0x3d49bf4e,0x3f803f18,0x3edbbf04,0x3f673f5c,0x3f673f5c,0xbedb3f04,
0x3f2c3f7d,0xbf3e3e16,0xbf3e3e16,0xbf2cbf7d,0x3e603f77,0xbf7abe89,0xbf58bf5f,0x3f09befc,0xbf6fbf42,0x3eb8bf27,0x3f6a3d97,0x3ecf3f7f,
0x3f51bdfb,0x3f133f7e,0xbe2f3f4a,0xbf7cbf1d,0x3cc93f65,0xbf80bee6,0xbf39bf73,0x3f31bea1,0x3dc93f75,0xbf7fbe95,0xbdc9bf75,0x3f7f3e95,
0xbf46bf62,0x3f22bef1,0x3f463f62,0xbf223ef1,0x3f7f3e95,0x3dc93f75,0xbf7fbe95,0xbdc9bf75,0xbf223ef1,0xbf46bf62,0x3f22bef1,0x3f463f62,
0xbcc93f73,0xbf80bea1,0x3f39bee6,0x3f313f65,0xbf09bf77,0x3f58be89,0xbe603f5f,0xbf7abefc,0x3f6a3f27,0xbecf3f42,0xbeb8bf7f,0x3f6fbd97,
0xbf7cbdfb,0xbe2fbf7e,0x3f513f4a,0xbf133f1d,0xbe163f71,0xbf7dbeac,0x3f7d3eac,0xbe163f71,0xbe79bf80,0x3f78bd49,0xbf783d49,0xbe79bf80,
0x3f183f67,0xbf4e3edb,0x3f4ebedb,0x3f183f67,0xbf5cbf2c,0x3f04bf3e,0xbf043f3e,0xbf5cbf2c,0xbe893f6f,0xbf77beb8,0x3efc3f6a,0xbf5f3ecf,
0x3d97bf7c,0x3f7f3e2f,0xbf27bf51,0x3f42bf13,0x3dfb3f80,0xbf7e3cc9,0x3f4a3f31,0xbf1d3f39,0xbea1bf7a,0x3f73be60,0xbf65bf09,0x3ee6bf58,
0xbec43f6d,0xbf6dbec4,0xbec43f6d,0xbf6dbec4,0x3ec4bf6d,0x3f6d3ec4,0x3ec4bf6d,0x3f6d3ec4,0xbec43f6d,0xbf6dbec4,0xbec43f6d,0xbf6dbec4,
0x3ec4bf6d,0x3f6d3ec4,0x3ec4bf6d,0x3f6d3ec4,0xbefc3f6a,0xbf5fbecf,0xbf773eb8,0xbe89bf6f,0x3f27bf51,0x3f423f13,0x3f7fbe2f,0x3d973f7c,
0xbf4a3f31,0xbf1dbf39,0xbf7ebcc9,0x3dfbbf80,0x3f65bf09,0x3ee63f58,0x3f733e60,0xbea13f7a,0xbf183f67,0xbf4ebedb,0xbf4ebedb,0x3f18bf67,
0x3f5cbf2c,0x3f043f3e,0x3f043f3e,0xbf5c3f2c,0xbf7d3eac,0xbe16bf71,0xbe16bf71,0x3f7dbeac,0x3f783d49,0xbe793f80,0xbe793f80,0xbf78bd49,
0xbf313f65,0xbf39bee6,0xbcc9bf73,0x3f80bea1,0x3f7abefc,0x3e603f5f,0xbf093f77,0xbf58be89,0xbf6fbd97,0x3eb8bf7f,0x3f6abf27,0x3ecf3f42,
0x3f133f1d,0xbf513f4a,0xbf7c3dfb,0x3e2fbf7e,0xbf463f62,0xbf22bef1,0x3f46bf62,0x3f223ef1,0x3f7fbe95,0xbdc93f75,0xbf7f3e95,0x3dc9bf75,
0xbf22bef1,0x3f46bf62,0x3f223ef1,0xbf463f62,0xbdc93f75,0xbf7f3e95,0x3dc9bf75,0x3f7fbe95,0xbf583f5f,0xbf09befc,0x3f7abe89,0xbe603f77,
0x3f6abd97,0xbecf3f7f,0xbeb8bf27,0x3f6fbf42,0xbe2fbf4a,0x3f7cbf1d,0xbf133f7e,0xbf51bdfb,0xbf393f73,0xbf31bea1,0x3f80bee6,0xbcc93f65,
0xbf673f5c,0xbedbbf04,0x3edb3f04,0xbf673f5c,0x3f3e3e16,0xbf2c3f7d,0x3f2cbf7d,0x3f3e3e16,0x3eacbf78,0x3f71be79,0xbf713e79,0x3eacbf78,
0xbf803f18,0xbd49bf4e,0x3d493f4e,0xbf803f18,0xbf733f58,0xbea1bf09,0xbee63f7a,0xbf653e60,0x3efc3eb8,0xbf5f3f6f,0x3f77becf,0xbe893f6a,
0x3f42bf7c,0x3f273e2f,0x3d97bf51,0x3f7fbf13,0xbf4a3cc9,0x3f1dbf80,0xbf7e3f39,0xbdfbbf31,0xbf7b3f55,0xbe48bf0e,0xbf7b3f55,0xbe48bf0e,
0x3e483f0e,0xbf7b3f55,0x3e483f0e,0xbf7b3f55,0x3f7bbf55,0x3e483f0e,0x3f7bbf55,0x3e483f0e,0xbe48bf0e,0x3f7bbf55,0xbe48bf0e,0x3f7bbf55,
0xbf7f3f51,0xbd97bf13,0xbf423e2f,0x3f27bf7c,0xbdfb3f39,0xbf7e3f31,0xbf4a3f80,0xbf1dbcc9,0x3f73bf09,0xbea13f58,0x3ee63e60,0xbf653f7a,
0x3efcbf6f,0x3f5fbeb8,0x3f77bf6a,0x3e893ecf,0xbf803f4e,0x3d49bf18,0x3d49bf18,0x3f80bf4e,0xbedb3f5c,0xbf673f04,0xbf673f04,0x3edbbf5c,
0x3f2cbe16,0xbf3e3f7d,0xbf3e3f7d,0xbf2c3e16,0x3f71bf78,0x3eac3e79,0x3eac3e79,0xbf713f78,0xbf7c3f4a,0x3e2fbf1d,0x3f51bf7e,0x3f13bdfb,
0xbf313f73,0xbf393ea1,0xbcc9bee6,0x3f80bf65,0x3e603e89,0xbf7a3f77,0xbf583efc,0x3f09bf5f,0x3f6fbf27,0xbeb83f42,0xbf6a3f7f,0xbecfbd97,
0xbf753f46,0x3e95bf22,0x3f75bf46,0xbe953f22,0xbf623f7f,0xbef13dc9,0x3f62bf7f,0x3ef1bdc9,0xbe953f22,0xbf753f46,0x3e95bf22,0x3f75bf46,
0x3ef1bdc9,0xbf623f7f,0xbef13dc9,0x3f62bf7f,0xbf6a3f42,0x3ecfbf27,0x3eb8bd97,0xbf6f3f7f,0xbf7c3f7e,0xbe2fbdfb,0x3f51bf1d,0xbf133f4a,
0xbf393f65,0xbf313ee6,0x3f80bf73,0xbcc93ea1,0xbe603efc,0xbf7a3f5f,0x3f58bf77,0x3f09be89,0xbf5c3f3e,0x3f04bf2c,0xbf043f2c,0xbf5c3f3e,
0xbf7d3f71,0x3e16beac,0xbe163eac,0xbf7d3f71,0xbf783f80,0xbe793d49,0x3e79bd49,0xbf783f80,0xbf4e3f67,0xbf183edb,0x3f18bedb,0xbf4e3f67,
0xbf4a3f39,0x3f1dbf31,0xbf7e3f80,0xbdfb3cc9,0xbf653f58,0x3ee6bf09,0xbf733f7a,0xbea13e60,0xbf773f6f,0x3e89beb8,0xbf5f3f6a,0xbefc3ecf,
0xbf7f3f7c,0x3d97be2f,0xbf423f51,0xbf273f13,0x3f803f80,0xbf353f35,0x3f803f80,0xbf353f35,0x3f803f80,0xbf353f35,0x3f803f80,0xbf353f35,
0x3f803f80,0xbf353f35,0x3f803f80,0xbf353f35,0x3f803f80,0xbf353f35,0x3f803f80,0xbf353f35,0xbdfbbcc9,0xbf7ebf80,0xbf4abf39,0xbf1dbf31,
0xbea1be60,0xbf73bf7a,0xbf65bf58,0xbee6bf09,0xbefcbecf,0xbf5fbf6a,0xbf77bf6f,0xbe89beb8,0xbf27bf13,0xbf42bf51,0xbf7fbf7c,0xbd97be2f,
0xbf78bf80,0x3e793d49,0x3e793d49,0x3f783f80,0xbf4ebf67,0x3f183edb,0x3f183edb,0x3f4e3f67,0xbf04bf2c,0x3f5c3f3e,0x3f5c3f3e,0x3f043f2c,
0xbe16beac,0x3f7d3f71,0x3f7d3f71,0x3e163eac,0x3eb83d97,0x3f6f3f7f,0x3ecf3f27,0xbf6abf42,0x3f513f1d,0x3f133f4a,0xbe2f3dfb,0xbf7cbf7e,
0x3f803f73,0x3cc93ea1,0xbf31bee6,0xbf39bf65,0x3f583f77,0xbf09be89,0xbf7abf5f,0xbe60befc,0x3f623f7f,0xbef1bdc9,0xbf62bf7f,0x3ef13dc9,
0x3e953f22,0xbf75bf46,0xbe95bf22,0x3f753f46,0xbef1bdc9,0xbf62bf7f,0x3ef13dc9,0x3f623f7f,0xbf75bf46,0xbe95bf22,0x3f753f46,0x3e953f22,
0xbf13bdfb,0xbf51bf7e,0x3f7c3f4a,0x3e2f3f1d,0xbf80bf65,0x3cc9bee6,0x3f313f73,0xbf39bea1,0xbf09bf5f,0x3f583efc,0xbe603e89,0xbf7abf77,
0x3ecfbd97,0x3f6a3f7f,0xbf6fbf27,0xbeb8bf42,0xbf3ebf7d,0x3f2c3e16,0xbf2cbe16,0xbf3ebf7d,0x3eacbe79,0x3f713f78,0xbf71bf78,0x3eacbe79,
0x3f803f4e,0x3d493f18,0xbd49bf18,0x3f803f4e,0x3edb3f5c,0xbf67bf04,0x3f673f04,0x3edb3f5c,0x3f423e2f,0x3f273f7c,0x3d97bf13,0x3f7f3f51,
0x3f4a3f80,0xbf1d3cc9,0x3f7e3f31,0x3dfb3f39,0xbee63e60,0xbf65bf7a,0x3ea13f58,0xbf73bf09,0xbf77bf6a,0x3e89becf,0xbf5fbeb8,0xbefcbf6f,
0x3f0e3f7b,0xbf55be48,0x3f0e3f7b,0xbf55be48,0xbf55be48,0xbf0ebf7b,0xbf55be48,0xbf0ebf7b,0xbf0ebf7b,0x3f553e48,0xbf0ebf7b,0x3f553e48,
0x3f553e48,0x3f0e3f7b,0x3f553e48,0x3f0e3f7b,0xbf65be60,0xbee6bf7a,0xbf73bf58,0x3ea1bf09,0xbe89bf6a,0x3f773ecf,0x3efcbeb8,0x3f5f3f6f,
0x3f7f3f13,0x3d973f51,0x3f423f7c,0xbf273e2f,0xbdfb3f31,0xbf7ebf39,0xbf4abcc9,0xbf1dbf80,0xbeacbf78,0x3f713e79,0x3f713e79,0x3eac3f78,
0x3f803f18,0xbd493f4e,0xbd493f4e,0xbf80bf18,0xbedb3f04,0xbf67bf5c,0xbf67bf5c,0x3edbbf04,0xbf2cbf7d,0x3f3ebe16,0x3f3ebe16,0x3f2c3f7d,
0x3f7a3e89,0x3e603f77,0xbf093efc,0xbf58bf5f,0xbeb83f27,0xbf6fbf42,0xbecfbf7f,0x3f6a3d97,0xbf13bf7e,0x3f51bdfb,0x3f7c3f1d,0xbe2f3f4a,
0x3f803ee6,0x3cc93f65,0xbf313ea1,0xbf39bf73,0x3dc93f75,0xbf7fbe95,0xbdc9bf75,0x3f7f3e95,0xbf46bf62,0x3f22bef1,0x3f463f62,0xbf223ef1,
0x3f7f3e95,0x3dc93f75,0xbf7fbe95,0xbdc9bf75,0xbf223ef1,0xbf46bf62,0x3f22bef1,0x3f463f62,0xbf80bea1,0x3cc9bf73,0x3f313f65,0xbf393ee6,
0x3f58be89,0x3f093f77,0xbf7abefc,0x3e60bf5f,0xbecf3f42,0xbf6abf27,0x3f6fbd97,0x3eb83f7f,0xbe2fbf7e,0x3f7c3dfb,0xbf133f1d,0xbf51bf4a,
0x3e16bf71,0x3f7d3eac,0xbf7dbeac,0x3e16bf71,0x3e793f80,0xbf783d49,0x3f78bd49,0x3e793f80,0xbf18bf67,0x3f4ebedb,0xbf4e3edb,0xbf18bf67,
0x3f5c3f2c,0xbf043f3e,0x3f04bf3e,0x3f5c3f2c,0x3f773eb8,0xbe893f6f,0x3f5fbecf,0x3efc3f6a,0xbf7fbe2f,0x3d97bf7c,0xbf423f13,0xbf27bf51,
0x3f7ebcc9,0x3dfb3f80,0x3f1dbf39,0x3f4a3f31,0xbf733e60,0xbea1bf7a,0xbee63f58,0xbf65bf09,0xbec43f6d,0xbf6dbec4,0xbec43f6d,0xbf6dbec4,
0x3ec4bf6d,0x3f6d3ec4,0x3ec4bf6d,0x3f6d3ec4,0xbec43f6d,0xbf6dbec4,0xbec43f6d,0xbf6dbec4,0x3ec4bf6d,0x3f6d3ec4,0x3ec4bf6d,0x3f6d3ec4,
0xbf5fbecf,0x3efcbf6a,0xbe89bf6f,0x3f77beb8,0x3f423f13,0xbf273f51,0x3d973f7c,0xbf7f3e2f,0xbf1dbf39,0x3f4abf31,0x3dfbbf80,0x3f7e3cc9,
0x3ee63f58,0xbf653f09,0xbea13f7a,0xbf73be60,0x3f18bf67,0x3f4e3edb,0x3f4e3edb,0xbf183f67,0xbf5c3f2c,0xbf04bf3e,0xbf04bf3e,0x3f5cbf2c,
0x3f7dbeac,0x3e163f71,0x3e163f71,0xbf7d3eac,0xbf78bd49,0x3e79bf80,0x3e79bf80,0x3f783d49,0x3f393ee6,0xbf313f65,0xbf803ea1,0xbcc9bf73,
0xbe60bf5f,0x3f7abefc,0x3f583e89,0xbf093f77,0xbeb83f7f,0xbf6fbd97,0xbecfbf42,0x3f6abf27,0x3f51bf4a,0x3f133f1d,0xbe2f3f7e,0xbf7c3dfb,
0xbf463f62,0xbf22bef1,0x3f46bf62,0x3f223ef1,0x3f7fbe95,0xbdc93f75,0xbf7f3e95,0x3dc9bf75,0xbf22bef1,0x3f46bf62,0x3f223ef1,0xbf463f62,
0xbdc93f75,0xbf7f3e95,0x3dc9bf75,0x3f7fbe95,0xbf09befc,0x3f58bf5f,0xbe603f77,0xbf7a3e89,0xbecf3f7f,0xbf6a3d97,0x3f6fbf42,0x3eb83f27,
0x3f7cbf1d,0x3e2f3f4a,0xbf51bdfb,0x3f13bf7e,0xbf31bea1,0x3f39bf73,0xbcc93f65,0xbf803ee6,0x3f67bf5c,0x3edb3f04,0xbedbbf04,0x3f67bf5c,
0xbf3ebe16,0x3f2cbf7d,0xbf2c3f7d,0xbf3ebe16,0xbeac3f78,0xbf713e79,0x3f71be79,0xbeac3f78,0x3f80bf18,0x3d493f4e,0xbd49bf4e,0x3f80bf18,
0x3ea13f09,0xbf733f58,0x3f65be60,0xbee63f7a,0x3f5fbf6f,0x3efc3eb8,0x3e89bf6a,0x3f77becf,0xbf27be2f,0x3f42bf7c,0xbf7f3f13,0x3d97bf51,
0xbf1d3f80,0xbf4a3cc9,0x3dfb3f31,0xbf7e3f39,0xbf7b3f55,0xbe48bf0e,0xbf7b3f55,0xbe48bf0e,0x3e483f0e,0xbf7b3f55,0x3e483f0e,0xbf7b3f55,
0x3f7bbf55,0x3e483f0e,0x3f7bbf55,0x3e483f0e,0xbe48bf0e,0x3f7bbf55,0xbe48bf0e,0x3f7bbf55,0xbd97bf13,0x3f7fbf51,0x3f27bf7c,0x3f42be2f,
0xbf7e3f31,0x3dfbbf39,0xbf1dbcc9,0x3f4abf80,0xbea13f58,0xbf733f09,0xbf653f7a,0xbee6be60,0x3f5fbeb8,0xbefc3f6f,0x3e893ecf,0xbf773f6a,
0x3f80bf4e,0xbd493f18,0xbd493f18,0xbf803f4e,0x3edbbf5c,0x3f67bf04,0x3f67bf04,0xbedb3f5c,0xbf2c3e16,0x3f3ebf7d,0x3f3ebf7d,0x3f2cbe16,
0xbf713f78,0xbeacbe79,0xbeacbe79,0x3f71bf78,0xbe2f3f1d,0xbf7c3f4a,0xbf133dfb,0x3f51bf7e,0x3f39bea1,0xbf313f73,0xbf803f65,0xbcc9bee6,
0x3f7abf77,0x3e603e89,0xbf093f5f,0xbf583efc,0x3eb8bf42,0x3f6fbf27,0x3ecf3d97,0xbf6a3f7f,0xbf753f46,0x3e95bf22,0x3f75bf46,0xbe953f22,
0xbf623f7f,0xbef13dc9,0x3f62bf7f,0x3ef1bdc9,0xbe953f22,0xbf753f46,0x3e95bf22,0x3f75bf46,0x3ef1bdc9,0xbf623f7f,0xbef13dc9,0x3f62bf7f,
0x3ecfbf27,0x3f6abf42,0xbf6f3f7f,0xbeb83d97,0xbe2fbdfb,0x3f7cbf7e,0xbf133f4a,0xbf513f1d,0xbf313ee6,0x3f39bf65,0xbcc93ea1,0xbf803f73,
0xbf7a3f5f,0x3e60befc,0x3f09be89,0xbf583f77,0x3f5cbf3e,0xbf043f2c,0x3f04bf2c,0x3f5cbf3e,0x3f7dbf71,0xbe163eac,0x3e16beac,0x3f7dbf71,
0x3f78bf80,0x3e79bd49,0xbe793d49,0x3f78bf80,0x3f4ebf67,0x3f18bedb,0xbf183edb,0x3f4ebf67,0xbf1d3f31,0xbf4a3f39,0x3dfbbcc9,0xbf7e3f80,
0xbee63f09,0xbf653f58,0x3ea1be60,0xbf733f7a,0xbe893eb8,0xbf773f6f,0x3efcbecf,0xbf5f3f6a,0xbd973e2f,0xbf7f3f7c,0x3f27bf13,0xbf423f51,
0x3f803f80,0xbf353f35,0x3f803f80,0xbf353f35,0x3f803f80,0xbf353f35,0x3f803f80,0xbf353f35,0x3f803f80,0xbf353f35,0x3f803f80,0xbf353f35,
0x3f803f80,0xbf353f35,0x3f803f80,0xbf353f35,0xbf7ebf80,0x3dfb3cc9,0xbf1dbf31,0x3f4a3f39,0xbf73bf7a,0x3ea13e60,0xbee6bf09,0x3f653f58,
0xbf5fbf6a,0x3efc3ecf,0xbe89beb8,0x3f773f6f,0xbf42bf51,0x3f273f13,0xbd97be2f,0x3f7f3f7c,0x3f783f80,0xbe79bd49,0xbe79bd49,0xbf78bf80,
0x3f4e3f67,0xbf18bedb,0xbf18bedb,0xbf4ebf67,0x3f043f2c,0xbf5cbf3e,0xbf5cbf3e,0xbf04bf2c,0x3e163eac,0xbf7dbf71,0xbf7dbf71,0xbe16beac,
0xbf6fbf7f,0x3eb83d97,0x3f6a3f42,0x3ecf3f27,0xbf13bf4a,0x3f513f1d,0x3f7c3f7e,0xbe2f3dfb,0xbcc9bea1,0x3f803f73,0x3f393f65,0xbf31bee6,
0x3f093e89,0x3f583f77,0x3e603efc,0xbf7abf5f,0x3f623f7f,0xbef1bdc9,0xbf62bf7f,0x3ef13dc9,0x3e953f22,0xbf75bf46,0xbe95bf22,0x3f753f46,
0xbef1bdc9,0xbf62bf7f,0x3ef13dc9,0x3f623f7f,0xbf75bf46,0xbe95bf22,0x3f753f46,0x3e953f22,0xbf51bf7e,0x3f133dfb,0x3e2f3f1d,0xbf7cbf4a,
0x3cc9bee6,0x3f803f65,0xbf39bea1,0xbf31bf73,0x3f583efc,0x3f093f5f,0xbf7abf77,0x3e60be89,0x3f6a3f7f,0xbecf3d97,0xbeb8bf42,0x3f6f3f27,
0x3f3e3f7d,0xbf2cbe16,0x3f2c3e16,0x3f3e3f7d,0xbeac3e79,0xbf71bf78,0x3f713f78,0xbeac3e79,0xbf80bf4e,0xbd49bf18,0x3d493f18,0xbf80bf4e,
0xbedbbf5c,0x3f673f04,0xbf67bf04,0xbedbbf5c,0xbf27bf7c,0x3f423e2f,0xbf7fbf51,0x3d97bf13,0x3f1dbcc9,0x3f4a3f80,0xbdfbbf39,0x3f7e3f31,
0x3f653f7a,0xbee63e60,0x3f733f09,0x3ea13f58,0xbe893ecf,0xbf77bf6a,0x3efc3f6f,0xbf5fbeb8,0x3f0e3f7b,0xbf55be48,0x3f0e3f7b,0xbf55be48,
0xbf55be48,0xbf0ebf7b,0xbf55be48,0xbf0ebf7b,0xbf0ebf7b,0x3f553e48,0xbf0ebf7b,0x3f553e48,0x3f553e48,0x3f0e3f7b,0x3f553e48,0x3f0e3f7b,
0xbee6bf7a,0x3f653e60,0x3ea1bf09,0x3f733f58,0x3f773ecf,0x3e893f6a,0x3f5f3f6f,0xbefc3eb8,0x3d973f51,0xbf7fbf13,0xbf273e2f,0xbf42bf7c,
0xbf7ebf39,0x3dfbbf31,0xbf1dbf80,0x3f4a3cc9,0x3eac3f78,0xbf71be79,0xbf71be79,0xbeacbf78,0xbf80bf18,0x3d49bf4e,0x3d49bf4e,0x3f803f18,
0x3edbbf04,0x3f673f5c,0x3f673f5c,0xbedb3f04,0x3f2c3f7d,0xbf3e3e16,0xbf3e3e16,0xbf2cbf7d,0xbe60bf77,0x3f7a3e89,0x3f583f5f,0xbf093efc,
0x3f6f3f42,0xbeb83f27,0xbf6abd97,0xbecfbf7f,0xbf513dfb,0xbf13bf7e,0x3e2fbf4a,0x3f7c3f1d,0xbcc9bf65,0x3f803ee6,0x3f393f73,0xbf313ea1,
0x3dc93f75,0xbf7fbe95,0xbdc9bf75,0x3f7f3e95,0xbf46bf62,0x3f22bef1,0x3f463f62,0xbf223ef1,0x3f7f3e95,0x3dc93f75,0xbf7fbe95,0xbdc9bf75,
0xbf223ef1,0xbf46bf62,0x3f22bef1,0x3f463f62,0x3cc9bf73,0x3f803ea1,0xbf393ee6,0xbf31bf65,0x3f093f77,0xbf583e89,0x3e60bf5f,0x3f7a3efc,
0xbf6abf27,0x3ecfbf42,0x3eb83f7f,0xbf6f3d97,0x3f7c3dfb,0x3e2f3f7e,0xbf51bf4a,0x3f13bf1d,0xbe163f71,0xbf7dbeac,0x3f7d3eac,0xbe163f71,
0xbe79bf80,0x3f78bd49,0xbf783d49,0xbe79bf80,0x3f183f67,0xbf4e3edb,0x3f4ebedb,0x3f183f67,0xbf5cbf2c,0x3f04bf3e,0xbf043f3e,0xbf5cbf2c,
0x3e89bf6f,0x3f773eb8,0xbefcbf6a,0x3f5fbecf,0xbd973f7c,0xbf7fbe2f,0x3f273f51,0xbf423f13,0xbdfbbf80,0x3f7ebcc9,0xbf4abf31,0x3f1dbf39,
0x3ea13f7a,0xbf733e60,0x3f653f09,0xbee63f58,0xbec43f6d,0xbf6dbec4,0xbec43f6d,0xbf6dbec4,0x3ec4bf6d,0x3f6d3ec4,0x3ec4bf6d,0x3f6d3ec4,
0xbec43f6d,0xbf6dbec4,0xbec43f6d,0xbf6dbec4,0x3ec4bf6d,0x3f6d3ec4,0x3ec4bf6d,0x3f6d3ec4,0x3efcbf6a,0x3f5f3ecf,0x3f77beb8,0x3e893f6f,
0xbf273f51,0xbf42bf13,0xbf7f3e2f,0xbd97bf7c,0x3f4abf31,0x3f1d3f39,0x3f7e3cc9,0xbdfb3f80,0xbf653f09,0xbee6bf58,0xbf73be60,0x3ea1bf7a,
0xbf183f67,0xbf4ebedb,0xbf4ebedb,0x3f18bf67,0x3f5cbf2c,0x3f043f3e,0x3f043f3e,0xbf5c3f2c,0xbf7d3eac,0xbe16bf71,0xbe16bf71,0x3f7dbeac,
0x3f783d49,0xbe793f80,0xbe793f80,0xbf78bd49,0x3f31bf65,0x3f393ee6,0x3cc93f73,0xbf803ea1,0xbf7a3efc,0xbe60bf5f,0x3f09bf77,0x3f583e89,
0x3f6f3d97,0xbeb83f7f,0xbf6a3f27,0xbecfbf42,0xbf13bf1d,0x3f51bf4a,0x3f7cbdfb,0xbe2f3f7e,0xbf463f62,0xbf22bef1,0x3f46bf62,0x3f223ef1,
0x3f7fbe95,0xbdc93f75,0xbf7f3e95,0x3dc9bf75,0xbf22bef1,0x3f46bf62,0x3f223ef1,0xbf463f62,0xbdc93f75,0xbf7f3e95,0x3dc9bf75,0x3f7fbe95,
0x3f58bf5f,0x3f093efc,0xbf7a3e89,0x3e60bf77,0xbf6a3d97,0x3ecfbf7f,0x3eb83f27,0xbf6f3f42,0x3e2f3f4a,0xbf7c3f1d,0x3f13bf7e,0x3f513dfb,
0x3f39bf73,0x3f313ea1,0xbf803ee6,0x3cc9bf65,0xbf673f5c,0xbedbbf04,0x3edb3f04,0xbf673f5c,0x3f3e3e16,0xbf2c3f7d,0x3f2cbf7d,0x3f3e3e16,
0x3eacbf78,0x3f71be79,0xbf713e79,0x3eacbf78,0xbf803f18,0xbd49bf4e,0x3d493f4e,0xbf803f18,0x3f73bf58,0x3ea13f09,0x3ee6bf7a,0x3f65be60,
0xbefcbeb8,0x3f5fbf6f,0xbf773ecf,0x3e89bf6a,0xbf423f7c,0xbf27be2f,0xbd973f51,0xbf7f3f13,0x3f4abcc9,0xbf1d3f80,0x3f7ebf39,0x3dfb3f31,
0xbf7b3f55,0xbe48bf0e,0xbf7b3f55,0xbe48bf0e,0x3e483f0e,0xbf7b3f55,0x3e483f0e,0xbf7b3f55,0x3f7bbf55,0x3e483f0e,0x3f7bbf55,0x3e483f0e,
0xbe48bf0e,0x3f7bbf55,0xbe48bf0e,0x3f7bbf55,0x3f7fbf51,0x3d973f13,0x3f42be2f,0xbf273f7c,0x3dfbbf39,0x3f7ebf31,0x3f4abf80,0x3f1d3cc9,
0xbf733f09,0x3ea1bf58,0xbee6be60,0x3f65bf7a,0xbefc3f6f,0xbf5f3eb8,0xbf773f6a,0xbe89becf,0xbf803f4e,0x3d49bf18,0x3d49bf18,0x3f80bf4e,
0xbedb3f5c,0xbf673f04,0xbf673f04,0x3edbbf5c,0x3f2cbe16,0xbf3e3f7d,0xbf3e3f7d,0xbf2c3e16,0x3f71bf78,0x3eac3e79,0x3eac3e79,0xbf713f78,
0x3f7cbf4a,0xbe2f3f1d,0xbf513f7e,0xbf133dfb,0x3f31bf73,0x3f39bea1,0x3cc93ee6,0xbf803f65,0xbe60be89,0x3f7abf77,0x3f58befc,0xbf093f5f,
0xbf6f3f27,0x3eb8bf42,0x3f6abf7f,0x3ecf3d97,0xbf753f46,0x3e95bf22,0x3f75bf46,0xbe953f22,0xbf623f7f,0xbef13dc9,0x3f62bf7f,0x3ef1bdc9,
0xbe953f22,0xbf753f46,0x3e95bf22,0x3f75bf46,0x3ef1bdc9,0xbf623f7f,0xbef13dc9,0x3f62bf7f,0x3f6abf42,0xbecf3f27,0xbeb83d97,0x3f6fbf7f,
0x3f7cbf7e,0x3e2f3dfb,0xbf513f1d,0x3f13bf4a,0x3f39bf65,0x3f31bee6,0xbf803f73,0x3cc9bea1,0x3e60befc,0x3f7abf5f,0xbf583f77,0xbf093e89,
0xbf5c3f3e,0x3f04bf2c,0xbf043f2c,0xbf5c3f3e,0xbf7d3f71,0x3e16beac,0xbe163eac,0xbf7d3f71,0xbf783f80,0xbe793d49,0x3e79bd49,0xbf783f80,
0xbf4e3f67,0xbf183edb,0x3f18bedb,0xbf4e3f67,0x3f4abf39,0xbf1d3f31,0x3f7ebf80,0x3dfbbcc9,0x3f65bf58,0xbee63f09,0x3f73bf7a,0x3ea1be60,
0x3f77bf6f,0xbe893eb8,0x3f5fbf6a,0x3efcbecf,0x3f7fbf7c,0xbd973e2f,0x3f42bf51,0x3f27bf13,0x3f803f80,0xbf353f35,0x3f803f80,0xbf353f35,
0x3f803f80,0xbf353f35,0x3f803f80,0xbf353f35,0x3f803f80,0xbf353f35,0x3f803f80,0xbf353f35,0x3f803f80,0xbf353f35,0x3f803f80,0xbf353f35,
0x3dfb3cc9,0x3f7e3f80,0x3f4a3f39,0x3f1d3f31,0x3ea13e60,0x3f733f7a,0x3f653f58,0x3ee63f09,0x3efc3ecf,0x3f5f3f6a,0x3f773f6f,0x3e893eb8,
0x3f273f13,0x3f423f51,0x3f7f3f7c,0x3d973e2f,0xbf78bf80,0x3e793d49,0x3e793d49,0x3f783f80,0xbf4ebf67,0x3f183edb,0x3f183edb,0x3f4e3f67,
0xbf04bf2c,0x3f5c3f3e,0x3f5c3f3e,0x3f043f2c,0xbe16beac,0x3f7d3f71,0x3f7d3f71,0x3e163eac,0xbeb8bd97,0xbf6fbf7f,0xbecfbf27,0x3f6a3f42,
0xbf51bf1d,0xbf13bf4a,0x3e2fbdfb,0x3f7c3f7e,0xbf80bf73,0xbcc9bea1,0x3f313ee6,0x3f393f65,0xbf58bf77,0x3f093e89,0x3f7a3f5f,0x3e603efc,
0x3f623f7f,0xbef1bdc9,0xbf62bf7f,0x3ef13dc9,0x3e953f22,0xbf75bf46,0xbe95bf22,0x3f753f46,0xbef1bdc9,0xbf62bf7f,0x3ef13dc9,0x3f623f7f,
0xbf75bf46,0xbe95bf22,0x3f753f46,0x3e953f22,0x3f133dfb,0x3f513f7e,0xbf7cbf4a,0xbe2fbf1d,0x3f803f65,0xbcc93ee6,0xbf31bf73,0x3f393ea1,
0x3f093f5f,0xbf58befc,0x3e60be89,0x3f7a3f77,0xbecf3d97,0xbf6abf7f,0x3f6f3f27,0x3eb83f42,0xbf3ebf7d,0x3f2c3e16,0xbf2cbe16,0xbf3ebf7d,
0x3eacbe79,0x3f713f78,0xbf71bf78,0x3eacbe79,0x3f803f4e,0x3d493f18,0xbd49bf18,0x3f803f4e,0x3edb3f5c,0xbf67bf04,0x3f673f04,0x3edb3f5c,
0xbf42be2f,0xbf27bf7c,0xbd973f13,0xbf7fbf51,0xbf4abf80,0x3f1dbcc9,0xbf7ebf31,0xbdfbbf39,0x3ee6be60,0x3f653f7a,0xbea1bf58,0x3f733f09,
0x3f773f6a,0xbe893ecf,0x3f5f3eb8,0x3efc3f6f,0x3f0e3f7b,0xbf55be48,0x3f0e3f7b,0xbf55be48,0xbf55be48,0xbf0ebf7b,0xbf55be48,0xbf0ebf7b,
0xbf0ebf7b,0x3f553e48,0xbf0ebf7b,0x3f553e48,0x3f553e48,0x3f0e3f7b,0x3f553e48,0x3f0e3f7b,0x3f653e60,0x3ee63f7a,0x3f733f58,0xbea13f09,
0x3e893f6a,0xbf77becf,0xbefc3eb8,0xbf5fbf6f,0xbf7fbf13,0xbd97bf51,0xbf42bf7c,0x3f27be2f,0x3dfbbf31,0x3f7e3f39,0x3f4a3cc9,0x3f1d3f80,
0xbeacbf78,0x3f713e79,0x3f713e79,0x3eac3f78,0x3f803f18,0xbd493f4e,0xbd493f4e,0xbf80bf18,0xbedb3f04,0xbf67bf5c,0xbf67bf5c,0x3edbbf04,
0xbf2cbf7d,0x3f3ebe16,0x3f3ebe16,0x3f2c3f7d,0xbf7abe89,0xbe60bf77,0x3f09befc,0x3f583f5f,0x3eb8bf27,0x3f6f3f42,0x3ecf3f7f,0xbf6abd97,
0x3f133f7e,0xbf513dfb,0xbf7cbf1d,0x3e2fbf4a,0xbf80bee6,0xbcc9bf65,0x3f31bea1,0x3f393f73,0x3dc93f75,0xbf7fbe95,0xbdc9bf75,0x3f7f3e95,
0xbf46bf62,0x3f22bef1,0x3f463f62,0xbf223ef1,0x3f7f3e95,0x3dc93f75,0xbf7fbe95,0xbdc9bf75,0xbf223ef1,0xbf46bf62,0x3f22bef1,0x3f463f62,
0x3f803ea1,0xbcc93f73,0xbf31bf65,0x3f39bee6,0xbf583e89,0xbf09bf77,0x3f7a3efc,0xbe603f5f,0x3ecfbf42,0x3f6a3f27,0xbf6f3d97,0xbeb8bf7f,
0x3e2f3f7e,0xbf7cbdfb,0x3f13bf1d,0x3f513f4a,0x3e16bf71,0x3f7d3eac,0xbf7dbeac,0x3e16bf71,0x3e793f80,0xbf783d49,0x3f78bd49,0x3e793f80,
0xbf18bf67,0x3f4ebedb,0xbf4e3edb,0xbf18bf67,0x3f5c3f2c,0xbf043f3e,0x3f04bf3e,0x3f5c3f2c,0xbf77beb8,0x3e89bf6f,0xbf5f3ecf,0xbefcbf6a,
0x3f7f3e2f,0xbd973f7c,0x3f42bf13,0x3f273f51,0xbf7e3cc9,0xbdfbbf80,0xbf1d3f39,0xbf4abf31,0x3f73be60,0x3ea13f7a,0x3ee6bf58,0x3f653f09,
0xbec43f6d,0xbf6dbec4,0xbec43f6d,0xbf6dbec4,0x3ec4bf6d,0x3f6d3ec4,0x3ec4bf6d,0x3f6d3ec4,0xbec43f6d,0xbf6dbec4,0xbec43f6d,0xbf6dbec4,
0x3ec4bf6d,0x3f6d3ec4,0x3ec4bf6d,0x3f6d3ec4,0x3f5f3ecf,0xbefc3f6a,0x3e893f6f,0xbf773eb8,0xbf42bf13,0x3f27bf51,0xbd97bf7c,0x3f7fbe2f,
0x3f1d3f39,0xbf4a3f31,0xbdfb3f80,0xbf7ebcc9,0xbee6bf58,0x3f65bf09,0x3ea1bf7a,0x3f733e60,0x3f18bf67,0x3f4e3edb,0x3f4e3edb,0xbf183f67,
0xbf5c3f2c,0xbf04bf3e,0xbf04bf3e,0x3f5cbf2c,0x3f7dbeac,0x3e163f71,0x3e163f71,0xbf7d3eac,0xbf78bd49,0x3e79bf80,0x3e79bf80,0x3f783d49,
0xbf39bee6,0x3f31bf65,0x3f80bea1,0x3cc93f73,0x3e603f5f,0xbf7a3efc,0xbf58be89,0x3f09bf77,0x3eb8bf7f,0x3f6f3d97,0x3ecf3f42,0xbf6a3f27,
0xbf513f4a,0xbf13bf1d,0x3e2fbf7e,0x3f7cbdfb,0xbf463f62,0xbf22bef1,0x3f46bf62,0x3f223ef1,0x3f7fbe95,0xbdc93f75,0xbf7f3e95,0x3dc9bf75,
0xbf22bef1,0x3f46bf62,0x3f223ef1,0xbf463f62,0xbdc93f75,0xbf7f3e95,0x3dc9bf75,0x3f7fbe95,0x3f093efc,0xbf583f5f,0x3e60bf77,0x3f7abe89,
0x3ecfbf7f,0x3f6abd97,0xbf6f3f42,0xbeb8bf27,0xbf7c3f1d,0xbe2fbf4a,0x3f513dfb,0xbf133f7e,0x3f313ea1,0xbf393f73,0x3cc9bf65,0x3f80bee6,
0x3f67bf5c,0x3edb3f04,0xbedbbf04,0x3f67bf5c,0xbf3ebe16,0x3f2cbf7d,0xbf2c3f7d,0xbf3ebe16,0xbeac3f78,0xbf713e79,0x3f71be79,0xbeac3f78,
0x3f80bf18,0x3d493f4e,0xbd49bf4e,0x3f80bf18,0xbea1bf09,0x3f73bf58,0xbf653e60,0x3ee6bf7a,0xbf5f3f6f,0xbefcbeb8,0xbe893f6a,0xbf773ecf,
0x3f273e2f,0xbf423f7c,0x3f7fbf13,0xbd973f51,0x3f1dbf80,0x3f4abcc9,0xbdfbbf31,0x3f7ebf39,0xbf7b3f55,0xbe48bf0e,0xbf7b3f55,0xbe48bf0e,
0x3e483f0e,0xbf7b3f55,0x3e483f0e,0xbf7b3f55,0x3f7bbf55,0x3e483f0e,0x3f7bbf55,0x3e483f0e,0xbe48bf0e,0x3f7bbf55,0xbe48bf0e,0x3f7bbf55,
0x3d973f13,0xbf7f3f51,0xbf273f7c,0xbf423e2f,0x3f7ebf31,0xbdfb3f39,0x3f1d3cc9,0xbf4a3f80,0x3ea1bf58,0x3f73bf09,0x3f65bf7a,0x3ee63e60,
0xbf5f3eb8,0x3efcbf6f,0xbe89becf,0x3f77bf6a,0x3f80bf4e,0xbd493f18,0xbd493f18,0xbf803f4e,0x3edbbf5c,0x3f67bf04,0x3f67bf04,0xbedb3f5c,
0xbf2c3e16,0x3f3ebf7d,0x3f3ebf7d,0x3f2cbe16,0xbf713f78,0xbeacbe79,0xbeacbe79,0x3f71bf78,0x3e2fbf1d,0x3f7cbf4a,0x3f13bdfb,0xbf513f7e,
0xbf393ea1,0x3f31bf73,0x3f80bf65,0x3cc93ee6,0xbf7a3f77,0xbe60be89,0x3f09bf5f,0x3f58befc,0xbeb83f42,0xbf6f3f27,0xbecfbd97,0x3f6abf7f,
0xbf753f46,0x3e95bf22,0x3f75bf46,0xbe953f22,0xbf623f7f,0xbef13dc9,0x3f62bf7f,0x3ef1bdc9,0xbe953f22,0xbf753f46,0x3e95bf22,0x3f75bf46,
0x3ef1bdc9,0xbf623f7f,0xbef13dc9,0x3f62bf7f,0xbecf3f27,0xbf6a3f42,0x3f6fbf7f,0x3eb8bd97,0x3e2f3dfb,0xbf7c3f7e,0x3f13bf4a,0x3f51bf1d,
0x3f31bee6,0xbf393f65,0x3cc9bea1,0x3f80bf73,0x3f7abf5f,0xbe603efc,0xbf093e89,0x3f58bf77,0x3f5cbf3e,0xbf043f2c,0x3f04bf2c,0x3f5cbf3e,
0x3f7dbf71,0xbe163eac,0x3e16beac,0x3f7dbf71,0x3f78bf80,0x3e79bd49,0xbe793d49,0x3f78bf80,0x3f4ebf67,0x3f18bedb,0xbf183edb,0x3f4ebf67,
0x3f1dbf31,0x3f4abf39,0xbdfb3cc9,0x3f7ebf80,0x3ee6bf09,0x3f65bf58,0xbea13e60,0x3f73bf7a,0x3e89beb8,0x3f77bf6f,0xbefc3ecf,0x3f5fbf6a,
0x3d97be2f,0x3f7fbf7c,0xbf273f13,0x3f42bf51,0x3f803f80,0xbf803f80,0x3f803f80,0xbf803f80,0x3f803f80,0xbf803f80,0x3f803f80,0xbf803f80,
0x3f803f80,0xbf803f80,0x3f803f80,0xbf803f80,0x3f803f80,0xbf803f80,0x3f803f80,0xbf803f80,0x3f7d3f80,0xbe16bd49,0x3f183f2c,0xbf4ebf3e,
0x3f713f78,0xbeacbe79,0x3edb3f04,0xbf67bf5c,0x3f5c3f67,0xbf04bedb,0x3e793eac,0xbf78bf71,0x3f3e3f4e,0xbf2cbf18,0x3d493e16,0xbf80bf7d,
0x3f753f7f,0xbe95bdc9,0xbe95bdc9,0xbf75bf7f,0x3f463f62,0xbf22bef1,0xbf22bef1,0xbf46bf62,0x3ef13f22,0xbf62bf46,0xbf62bf46,0xbef1bf22,
0x3dc93e95,0xbf7fbf75,0xbf7fbf75,0xbdc9be95,0x3f673f7d,0xbedbbe16,0xbf71bf4e,0xbeacbf18,0x3f043f3e,0xbf5cbf2c,0xbf78bf80,0x3e79bd49,
0xbd493e79,0xbf80bf78,0xbf2cbf5c,0x3f3e3f04,0xbf18beac,0xbf4ebf71,0xbe16bedb,0x3f7d3f67,0x3f553f7b,0xbf0ebe48,0xbf55bf7b,0x3f0e3e48,
0x3e483f0e,0xbf7bbf55,0xbe48bf0e,0x3f7b3f55,0xbf0ebe48,0xbf55bf7b,0x3f0e3e48,0x3f553f7b,0xbf7bbf55,0xbe48bf0e,0x3f7b3f55,0x3e483f0e,
0x3f3e3f78,0xbf2cbe79,0xbd49bf04,0x3f803f5c,0xbe163eac,0xbf7dbf71,0x3f4e3edb,0x3f183f67,0xbf67bf18,0xbedbbf4e,0x3f713f7d,0xbeac3e16,
0xbf5cbf80,0x3f043d49,0x3e793f2c,0xbf78bf3e,0x3f223f75,0xbf46be95,0x3f463e95,0x3f223f75,0xbef13dc9,0xbf62bf7f,0x3f623f7f,0xbef13dc9,
0xbf7fbf62,0x3dc9bef1,0xbdc93ef1,0xbf7fbf62,0xbe95bf46,0x3f753f22,0xbf75bf22,0xbe95bf46,0x3f043f71,0xbf5cbeac,0x3f783f67,0xbe793edb,
0xbf3ebe16,0xbf2cbf7d,0xbd493f18,0xbf80bf4e,0xbf4ebf80,0x3f18bd49,0xbf7dbf2c,0xbe16bf3e,0x3edbbe79,0x3f673f78,0xbeacbf5c,0x3f713f04,
0x3ec43f6d,0xbf6dbec4,0x3ec43f6d,0xbf6dbec4,0xbf6dbec4,0xbec4bf6d,0xbf6dbec4,0xbec4bf6d,0xbec4bf6d,0x3f6d3ec4,0xbec4bf6d,0x3f6d3ec4,
0x3f6d3ec4,0x3ec43f6d,0x3f6d3ec4,0x3ec43f6d,0x3e793f67,0xbf78bedb,0xbf043eac,0xbf5cbf71,0xbf80bf18,0xbd49bf4e,0xbf3ebf7d,0x3f2cbe16,
0x3e16bf2c,0x3f7d3f3e,0x3f4e3d49,0x3f183f80,0x3f713f5c,0xbeac3f04,0x3edb3f78,0xbf67be79,0x3dc93f62,0xbf7fbef1,0xbf7fbef1,0xbdc9bf62,
0xbf75bf46,0x3e95bf22,0x3e95bf22,0x3f753f46,0x3f22be95,0x3f463f75,0x3f463f75,0xbf223e95,0x3ef13f7f,0xbf62bdc9,0xbf62bdc9,0xbef1bf7f,
0xbd493f5c,0xbf80bf04,0xbf2cbf78,0x3f3ebe79,0xbf4ebf67,0x3f18bedb,0x3f7d3eac,0x3e163f71,0x3f713e16,0x3eac3f7d,0xbedb3f18,0xbf67bf4e,
0xbe793f3e,0xbf78bf2c,0xbf04bf80,0x3f5cbd49,0xbe483f55,0xbf7bbf0e,0x3e48bf55,0x3f7b3f0e,0xbf0ebf7b,0x3f55be48,0x3f0e3f7b,0xbf553e48,
0x3f7b3f0e,0xbe483f55,0xbf7bbf0e,0x3e48bf55,0xbf553e48,0xbf0ebf7b,0x3f55be48,0x3f0e3f7b,0xbeac3f4e,0xbf71bf18,0x3f67be16,0x3edb3f7d,
0xbe79bf80,0x3f783d49,0xbf043f2c,0xbf5cbf3e,0x3f3e3f5c,0xbf2c3f04,0xbd49bf78,0x3f803e79,0xbf7dbedb,0x3e16bf67,0x3f183f71,0xbf4e3eac,
0xbef13f46,0xbf62bf22,0x3f623f22,0xbef13f46,0x3dc9bf75,0x3f7f3e95,0xbf7fbe95,0x3dc9bf75,0x3e953f7f,0xbf753dc9,0x3f75bdc9,0x3e953f7f,
0xbf22bf62,0x3f46bef1,0xbf463ef1,0xbf22bf62,0xbf183f3e,0xbf4ebf2c,0x3e163f80,0xbf7d3d49,0x3edbbf5c,0x3f673f04,0xbeacbf78,0x3f71be79,
0xbe793f71,0xbf78beac,0x3f043f67,0xbf5c3edb,0x3d49bf7d,0x3f803e16,0xbf2cbf4e,0x3f3ebf18,0xbf353f35,0xbf35bf35,0xbf353f35,0xbf35bf35,
0x3f35bf35,0x3f353f35,0x3f35bf35,0x3f353f35,0xbf353f35,0xbf35bf35,0xbf353f35,0xbf35bf35,0x3f35bf35,0x3f353f35,0x3f35bf35,0x3f353f35,
0xbf4e3f2c,0xbf18bf3e,0xbf7dbd49,0x3e16bf80,0x3f67bf04,0x3edb3f5c,0x3f713e79,0xbeac3f78,0xbf783eac,0xbe79bf71,0xbf5cbedb,0x3f04bf67,
0x3f80be16,0x3d493f7d,0x3f3e3f18,0xbf2c3f4e,0xbf623f22,0xbef1bf46,0xbef1bf46,0x3f62bf22,0x3f7fbe95,0x3dc93f75,0x3dc93f75,0xbf7f3e95,
0xbf75bdc9,0x3e95bf7f,0x3e95bf7f,0x3f753dc9,0x3f463ef1,0xbf223f62,0xbf223f62,0xbf46bef1,0xbf713f18,0xbeacbf4e,0x3edbbf7d,0x3f673e16,
0x3f78bd49,0xbe793f80,0xbf5c3f3e,0xbf04bf2c,0xbf2cbf04,0x3f3ebf5c,0x3f80be79,0xbd493f78,0x3e163f67,0xbf7d3edb,0xbf4ebeac,0x3f18bf71,
0xbf7b3f0e,0xbe48bf55,0x3f7bbf0e,0x3e483f55,0x3f553e48,0xbf0e3f7b,0xbf55be48,0x3f0ebf7b,0xbe48bf55,0x3f7bbf0e,0x3e483f55,0xbf7b3f0e,
0xbf0e3f7b,0xbf55be48,0x3f0ebf7b,0x3f553e48,0xbf803f04,0xbd49bf5c,0x3f3e3e79,0xbf2c3f78,0x3f183edb,0xbf4e3f67,0x3e16bf71,0x3f7dbeac,
0x3eacbf7d,0x3f71be16,0xbf673f4e,0xbedbbf18,0xbf783f2c,0xbe79bf3e,0x3f5c3d49,0xbf043f80,0xbf7f3ef1,0x3dc9bf62,0xbdc93f62,0xbf7f3ef1,
0x3e953f22,0xbf753f46,0x3f75bf46,0x3e953f22,0x3f46bf75,0x3f223e95,0xbf22be95,0x3f46bf75,0xbf623dc9,0x3ef1bf7f,0xbef13f7f,0xbf623dc9,
0xbf783edb,0x3e79bf67,0xbf5c3f71,0xbf04beac,0xbd493f4e,0xbf803f18,0x3f2c3e16,0xbf3e3f7d,0x3f7dbf3e,0x3e163f2c,0x3f18bf80,0x3f4ebd49,
0xbeacbf04,0x3f71bf5c,0xbf673e79,0x3edbbf78,0xbf6d3ec4,0x3ec4bf6d,0xbf6d3ec4,0x3ec4bf6d,0xbec43f6d,0xbf6d3ec4,0xbec43f6d,0xbf6d3ec4,
0x3f6dbec4,0xbec43f6d,0x3f6dbec4,0xbec43f6d,0x3ec4bf6d,0x3f6dbec4,0x3ec4bf6d,0x3f6dbec4,0xbf5c3eac,0x3f04bf71,0xbe79bedb,0x3f78bf67,
0xbf2c3f7d,0xbf3e3e16,0xbf803f4e,0xbd49bf18,0x3f183d49,0xbf4e3f80,0xbe163f3e,0xbf7d3f2c,0x3f67bf78,0x3edb3e79,0x3f71bf04,0xbeac3f5c,
0xbf463e95,0x3f22bf75,0x3f22bf75,0x3f46be95,0xbf623f7f,0xbef1bdc9,0xbef1bdc9,0x3f62bf7f,0x3dc93ef1,0xbf7f3f62,0xbf7f3f62,0xbdc9bef1,
0x3f75bf22,0xbe953f46,0xbe953f46,0xbf753f22,0xbf2c3e79,0x3f3ebf78,0x3f80bf5c,0xbd493f04,0xbf7d3f71,0xbe16beac,0x3f18bf67,0x3f4ebedb,
0xbedb3f4e,0xbf673f18,0xbeacbe16,0x3f71bf7d,0x3f04bd49,0xbf5c3f80,0xbf783f3e,0x3e79bf2c,0xbf0e3e48,0x3f55bf7b,0x3f0ebe48,0xbf553f7b,
0xbf7b3f55,0x3e48bf0e,0x3f7bbf55,0xbe483f0e,0xbf553f7b,0xbf0e3e48,0x3f55bf7b,0x3f0ebe48,0xbe483f0e,0xbf7b3f55,0x3e48bf0e,0x3f7bbf55,
0xbedb3e16,0x3f67bf7d,0xbeac3f18,0xbf713f4e,0xbf5c3f2c,0x3f04bf3e,0x3e793d49,0xbf783f80,0xbf803f78,0xbd49be79,0x3f3ebf04,0xbf2c3f5c,
0xbf4e3f71,0xbf183eac,0x3f7dbf67,0xbe163edb,0xbe953dc9,0x3f75bf7f,0xbf753f7f,0xbe953dc9,0xbf223ef1,0x3f46bf62,0xbf463f62,0xbf223ef1,
0xbf623f46,0x3ef1bf22,0xbef13f22,0xbf623f46,0xbf7f3f75,0x3dc9be95,0xbdc93e95,0xbf7f3f75,0xbe163d49,0x3f7dbf80,0xbf4e3f3e,0x3f18bf2c,
0xbeac3e79,0x3f71bf78,0xbf673f5c,0x3edbbf04,0xbf043edb,0x3f5cbf67,0xbf783f71,0x3e79beac,0xbf2c3f18,0x3f3ebf4e,0xbf803f7d,0x3d49be16,
0x3f803f80,0xbf803f80,0x3f803f80,0xbf803f80,0x3f803f80,0xbf803f80,0x3f803f80,0xbf803f80,0x3f803f80,0xbf803f80,0x3f803f80,0xbf803f80,
0x3f803f80,0xbf803f80,0x3f803f80,0xbf803f80,0xbe16bd49,0xbf7dbf80,0xbf4ebf3e,0xbf18bf2c,0xbeacbe79,0xbf71bf78,0xbf67bf5c,0xbedbbf04,
0xbf04bedb,0xbf5cbf67,0xbf78bf71,0xbe79beac,0xbf2cbf18,0xbf3ebf4e,0xbf80bf7d,0xbd49be16,0xbf75bf7f,0x3e953dc9,0x3e953dc9,0x3f753f7f,
0xbf46bf62,0x3f223ef1,0x3f223ef1,0x3f463f62,0xbef1bf22,0x3f623f46,0x3f623f46,0x3ef13f22,0xbdc9be95,0x3f7f3f75,0x3f7f3f75,0x3dc93e95,
0x3edb3e16,0x3f673f7d,0x3eac3f18,0xbf71bf4e,0x3f5c3f2c,0x3f043f3e,0xbe793d49,0xbf78bf80,0x3f803f78,0xbd493e79,0xbf3ebf04,0xbf2cbf5c,
0x3f4e3f71,0xbf18beac,0xbf7dbf67,0xbe16bedb,0x3f553f7b,0xbf0ebe48,0xbf55bf7b,0x3f0e3e48,0x3e483f0e,0xbf7bbf55,0xbe48bf0e,0x3f7b3f55,
0xbf0ebe48,0xbf55bf7b,0x3f0e3e48,0x3f553f7b,0xbf7bbf55,0xbe48bf0e,0x3f7b3f55,0x3e483f0e,0xbf2cbe79,0xbf3ebf78,0x3f803f5c,0x3d493f04,
0xbf7dbf71,0x3e16beac,0x3f183f67,0xbf4ebedb,0xbedbbf4e,0x3f673f18,0xbeac3e16,0xbf71bf7d,0x3f043d49,0x3f5c3f80,0xbf78bf3e,0xbe79bf2c,
0xbf22bf75,0x3f463e95,0xbf46be95,0xbf22bf75,0x3ef1bdc9,0x3f623f7f,0xbf62bf7f,0x3ef1bdc9,0x3f7f3f62,0xbdc93ef1,0x3dc9bef1,0x3f7f3f62,
0x3e953f46,0xbf75bf22,0x3f753f22,0x3e953f46,0x3f5c3eac,0x3f043f71,0x3e79bedb,0x3f783f67,0x3f2c3f7d,0xbf3ebe16,0x3f803f4e,0xbd493f18,
0xbf183d49,0xbf4ebf80,0x3e163f3e,0xbf7dbf2c,0xbf67bf78,0x3edbbe79,0xbf71bf04,0xbeacbf5c,0x3ec43f6d,0xbf6dbec4,0x3ec43f6d,0xbf6dbec4,
0xbf6dbec4,0xbec4bf6d,0xbf6dbec4,0xbec4bf6d,0xbec4bf6d,0x3f6d3ec4,0xbec4bf6d,0x3f6d3ec4,0x3f6d3ec4,0x3ec43f6d,0x3f6d3ec4,0x3ec43f6d,
0xbf78bedb,0xbe79bf67,0xbf5cbf71,0x3f04beac,0xbd49bf4e,0x3f803f18,0x3f2cbe16,0x3f3e3f7d,0x3f7d3f3e,0xbe163f2c,0x3f183f80,0xbf4ebd49,
0xbeac3f04,0xbf71bf5c,0xbf67be79,0xbedbbf78,0xbdc9bf62,0x3f7f3ef1,0x3f7f3ef1,0x3dc93f62,0x3f753f46,0xbe953f22,0xbe953f22,0xbf75bf46,
0xbf223e95,0xbf46bf75,0xbf46bf75,0x3f22be95,0xbef1bf7f,0x3f623dc9,0x3f623dc9,0x3ef13f7f,0x3f803f04,0xbd493f5c,0xbf3e3e79,0xbf2cbf78,
0xbf183edb,0xbf4ebf67,0xbe16bf71,0x3f7d3eac,0xbeacbf7d,0x3f713e16,0x3f673f4e,0xbedb3f18,0x3f783f2c,0xbe793f3e,0xbf5c3d49,0xbf04bf80,
0xbe483f55,0xbf7bbf0e,0x3e48bf55,0x3f7b3f0e,0xbf0ebf7b,0x3f55be48,0x3f0e3f7b,0xbf553e48,0x3f7b3f0e,0xbe483f55,0xbf7bbf0e,0x3e48bf55,
0xbf553e48,0xbf0ebf7b,0x3f55be48,0x3f0e3f7b,0xbf71bf18,0x3eacbf4e,0x3edb3f7d,0xbf673e16,0x3f783d49,0x3e793f80,0xbf5cbf3e,0x3f04bf2c,
0xbf2c3f04,0xbf3ebf5c,0x3f803e79,0x3d493f78,0x3e16bf67,0x3f7d3edb,0xbf4e3eac,0xbf18bf71,0x3ef1bf46,0x3f623f22,0xbf62bf22,0x3ef1bf46,
0xbdc93f75,0xbf7fbe95,0x3f7f3e95,0xbdc93f75,0xbe95bf7f,0x3f75bdc9,0xbf753dc9,0xbe95bf7f,0x3f223f62,0xbf463ef1,0x3f46bef1,0x3f223f62,
0x3f4e3f2c,0xbf183f3e,0x3f7dbd49,0x3e163f80,0xbf67bf04,0x3edbbf5c,0xbf713e79,0xbeacbf78,0x3f783eac,0xbe793f71,0x3f5cbedb,0x3f043f67,
0xbf80be16,0x3d49bf7d,0xbf3e3f18,0xbf2cbf4e,0xbf353f35,0xbf35bf35,0xbf353f35,0xbf35bf35,0x3f35bf35,0x3f353f35,0x3f35bf35,0x3f353f35,
0xbf353f35,0xbf35bf35,0xbf353f35,0xbf35bf35,0x3f35bf35,0x3f353f35,0x3f35bf35,0x3f353f35,0xbf18bf3e,0x3f4ebf2c,0x3e16bf80,0x3f7d3d49,
0x3edb3f5c,0xbf673f04,0xbeac3f78,0xbf71be79,0xbe79bf71,0x3f78beac,0x3f04bf67,0x3f5c3edb,0x3d493f7d,0xbf803e16,0xbf2c3f4e,0xbf3ebf18,
0x3f62bf22,0x3ef13f46,0x3ef13f46,0xbf623f22,0xbf7f3e95,0xbdc9bf75,0xbdc9bf75,0x3f7fbe95,0x3f753dc9,0xbe953f7f,0xbe953f7f,0xbf75bdc9,
0xbf46bef1,0x3f22bf62,0x3f22bf62,0x3f463ef1,0x3eac3f4e,0xbf713f18,0xbf67be16,0x3edbbf7d,0x3e79bf80,0x3f78bd49,0x3f043f2c,0xbf5c3f3e,
0xbf3e3f5c,0xbf2cbf04,0x3d49bf78,0x3f80be79,0x3f7dbedb,0x3e163f67,0xbf183f71,0xbf4ebeac,0xbf7b3f0e,0xbe48bf55,0x3f7bbf0e,0x3e483f55,
0x3f553e48,0xbf0e3f7b,0xbf55be48,0x3f0ebf7b,0xbe48bf55,0x3f7bbf0e,0x3e483f55,0xbf7b3f0e,0xbf0e3f7b,0xbf55be48,0x3f0ebf7b,0x3f553e48,
0xbd49bf5c,0x3f80bf04,0xbf2c3f78,0xbf3ebe79,0xbf4e3f67,0xbf18bedb,0x3f7dbeac,0xbe163f71,0x3f71be16,0xbeac3f7d,0xbedbbf18,0x3f67bf4e,
0xbe79bf3e,0x3f78bf2c,0xbf043f80,0xbf5cbd49,0x3f7fbef1,0xbdc93f62,0x3dc9bf62,0x3f7fbef1,0xbe95bf22,0x3f75bf46,0xbf753f46,0xbe95bf22,
0xbf463f75,0xbf22be95,0x3f223e95,0xbf463f75,0x3f62bdc9,0xbef13f7f,0x3ef1bf7f,0x3f62bdc9,0xbe793f67,0xbf783edb,0x3f043eac,0xbf5c3f71,
0x3f80bf18,0xbd493f4e,0x3f3ebf7d,0x3f2c3e16,0xbe16bf2c,0x3f7dbf3e,0xbf4e3d49,0x3f18bf80,0xbf713f5c,0xbeacbf04,0xbedb3f78,0xbf673e79,
0xbf6d3ec4,0x3ec4bf6d,0xbf6d3ec4,0x3ec4bf6d,0xbec43f6d,0xbf6d3ec4,0xbec43f6d,0xbf6d3ec4,0x3f6dbec4,0xbec43f6d,0x3f6dbec4,0xbec43f6d,
0x3ec4bf6d,0x3f6dbec4,0x3ec4bf6d,0x3f6dbec4,0x3f04bf71,0x3f5cbeac,0x3f78bf67,0x3e793edb,0xbf3e3e16,0x3f2cbf7d,0xbd49bf18,0x3f80bf4e,
0xbf4e3f80,0xbf18bd49,0xbf7d3f2c,0x3e16bf3e,0x3edb3e79,0xbf673f78,0xbeac3f5c,0xbf713f04,0x3f46be95,0xbf223f75,0xbf223f75,0xbf463e95,
0x3f62bf7f,0x3ef13dc9,0x3ef13dc9,0xbf623f7f,0xbdc9bef1,0x3f7fbf62,0x3f7fbf62,0x3dc93ef1,0xbf753f22,0x3e95bf46,0x3e95bf46,0x3f75bf22,
0xbf3e3f78,0xbf2c3e79,0x3d49bf04,0x3f80bf5c,0x3e163eac,0xbf7d3f71,0xbf4e3edb,0x3f18bf67,0x3f67bf18,0xbedb3f4e,0xbf713f7d,0xbeacbe16,
0x3f5cbf80,0x3f04bd49,0xbe793f2c,0xbf783f3e,0xbf0e3e48,0x3f55bf7b,0x3f0ebe48,0xbf553f7b,0xbf7b3f55,0x3e48bf0e,0x3f7bbf55,0xbe483f0e,
0xbf553f7b,0xbf0e3e48,0x3f55bf7b,0x3f0ebe48,0xbe483f0e,0xbf7b3f55,0x3e48bf0e,0x3f7bbf55,0x3f67bf7d,0x3edbbe16,0xbf713f4e,0x3eacbf18,
0x3f04bf3e,0x3f5cbf2c,0xbf783f80,0xbe79bd49,0xbd49be79,0x3f80bf78,0xbf2c3f5c,0xbf3e3f04,0xbf183eac,0x3f4ebf71,0xbe163edb,0xbf7d3f67,
0x3e95bdc9,0xbf753f7f,0x3f75bf7f,0x3e95bdc9,0x3f22bef1,0xbf463f62,0x3f46bf62,0x3f22bef1,0x3f62bf46,0xbef13f22,0x3ef1bf22,0x3f62bf46,
0x3f7fbf75,0xbdc93e95,0x3dc9be95,0x3f7fbf75,0xbf7d3f80,0xbe163d49,0xbf183f2c,0xbf4e3f3e,0xbf713f78,0xbeac3e79,0xbedb3f04,0xbf673f5c,
0xbf5c3f67,0xbf043edb,0xbe793eac,0xbf783f71,0xbf3e3f4e,0xbf2c3f18,0xbd493e16,0xbf803f7d,0x3f803f80,0xbf803f80,0x3f803f80,0xbf803f80,
0x3f803f80,0xbf803f80,0x3f803f80,0xbf803f80,0x3f803f80,0xbf803f80,0x3f803f80,0xbf803f80,0x3f803f80,0xbf803f80,0x3f803f80,0xbf803f80,
0xbf7dbf80,0x3e163d49,0xbf18bf2c,0x3f4e3f3e,0xbf71bf78,0x3eac3e79,0xbedbbf04,0x3f673f5c,0xbf5cbf67,0x3f043edb,0xbe79beac,0x3f783f71,
0xbf3ebf4e,0x3f2c3f18,0xbd49be16,0x3f803f7d,0x3f753f7f,0xbe95bdc9,0xbe95bdc9,0xbf75bf7f,0x3f463f62,0xbf22bef1,0xbf22bef1,0xbf46bf62,
0x3ef13f22,0xbf62bf46,0xbf62bf46,0xbef1bf22,0x3dc93e95,0xbf7fbf75,0xbf7fbf75,0xbdc9be95,0xbf67bf7d,0x3edb3e16,0x3f713f4e,0x3eac3f18,
0xbf04bf3e,0x3f5c3f2c,0x3f783f80,0xbe793d49,0x3d49be79,0x3f803f78,0x3f2c3f5c,0xbf3ebf04,0x3f183eac,0x3f4e3f71,0x3e163edb,0xbf7dbf67,
0x3f553f7b,0xbf0ebe48,0xbf55bf7b,0x3f0e3e48,0x3e483f0e,0xbf7bbf55,0xbe48bf0e,0x3f7b3f55,0xbf0ebe48,0xbf55bf7b,0x3f0e3e48,0x3f553f7b,
0xbf7bbf55,0xbe48bf0e,0x3f7b3f55,0x3e483f0e,0xbf3ebf78,0x3f2c3e79,0x3d493f04,0xbf80bf5c,0x3e16beac,0x3f7d3f71,0xbf4ebedb,0xbf18bf67,
0x3f673f18,0x3edb3f4e,0xbf71bf7d,0x3eacbe16,0x3f5c3f80,0xbf04bd49,0xbe79bf2c,0x3f783f3e,0x3f223f75,0xbf46be95,0x3f463e95,0x3f223f75,
0xbef13dc9,0xbf62bf7f,0x3f623f7f,0xbef13dc9,0xbf7fbf62,0x3dc9bef1,0xbdc93ef1,0xbf7fbf62,0xbe95bf46,0x3f753f22,0xbf75bf22,0xbe95bf46,
0xbf04bf71,0x3f5c3eac,0xbf78bf67,0x3e79bedb,0x3f3e3e16,0x3f2c3f7d,0x3d49bf18,0x3f803f4e,0x3f4e3f80,0xbf183d49,0x3f7d3f2c,0x3e163f3e,
0xbedb3e79,0xbf67bf78,0x3eac3f5c,0xbf71bf04,0x3ec43f6d,0xbf6dbec4,0x3ec43f6d,0xbf6dbec4,0xbf6dbec4,0xbec4bf6d,0xbf6dbec4,0xbec4bf6d,
0xbec4bf6d,0x3f6d3ec4,0xbec4bf6d,0x3f6d3ec4,0x3f6d3ec4,0x3ec43f6d,0x3f6d3ec4,0x3ec43f6d,0xbe79bf67,0x3f783edb,0x3f04beac,0x3f5c3f71,
0x3f803f18,0x3d493f4e,0x3f3e3f7d,0xbf2c3e16,0xbe163f2c,0xbf7dbf3e,0xbf4ebd49,0xbf18bf80,0xbf71bf5c,0x3eacbf04,0xbedbbf78,0x3f673e79,
0x3dc93f62,0xbf7fbef1,0xbf7fbef1,0xbdc9bf62,0xbf75bf46,0x3e95bf22,0x3e95bf22,0x3f753f46,0x3f22be95,0x3f463f75,0x3f463f75,0xbf223e95,
0x3ef13f7f,0xbf62bdc9,0xbf62bdc9,0xbef1bf7f,0x3d49bf5c,0x3f803f04,0x3f2c3f78,0xbf3e3e79,0x3f4e3f67,0xbf183edb,0xbf7dbeac,0xbe16bf71,
0xbf71be16,0xbeacbf7d,0x3edbbf18,0x3f673f4e,0x3e79bf3e,0x3f783f2c,0x3f043f80,0xbf5c3d49,0xbe483f55,0xbf7bbf0e,0x3e48bf55,0x3f7b3f0e,
0xbf0ebf7b,0x3f55be48,0x3f0e3f7b,0xbf553e48,0x3f7b3f0e,0xbe483f55,0xbf7bbf0e,0x3e48bf55,0xbf553e48,0xbf0ebf7b,0x3f55be48,0x3f0e3f7b,
0x3eacbf4e,0x3f713f18,0xbf673e16,0xbedbbf7d,0x3e793f80,0xbf78bd49,0x3f04bf2c,0x3f5c3f3e,0xbf3ebf5c,0x3f2cbf04,0x3d493f78,0xbf80be79,
0x3f7d3edb,0xbe163f67,0xbf18bf71,0x3f4ebeac,0xbef13f46,0xbf62bf22,0x3f623f22,0xbef13f46,0x3dc9bf75,0x3f7f3e95,0xbf7fbe95,0x3dc9bf75,
0x3e953f7f,0xbf753dc9,0x3f75bdc9,0x3e953f7f,0xbf22bf62,0x3f46bef1,0xbf463ef1,0xbf22bf62,0x3f18bf3e,0x3f4e3f2c,0xbe16bf80,0x3f7dbd49,
0xbedb3f5c,0xbf67bf04,0x3eac3f78,0xbf713e79,0x3e79bf71,0x3f783eac,0xbf04bf67,0x3f5cbedb,0xbd493f7d,0xbf80be16,0x3f2c3f4e,0xbf3e3f18,
0xbf353f35,0xbf35bf35,0xbf353f35,0xbf35bf35,0x3f35bf35,0x3f353f35,0x3f35bf35,0x3f353f35,0xbf353f35,0xbf35bf35,0xbf353f35,0xbf35bf35,
0x3f35bf35,0x3f353f35,0x3f35bf35,0x3f353f35,0x3f4ebf2c,0x3f183f3e,0x3f7d3d49,0xbe163f80,0xbf673f04,0xbedbbf5c,0xbf71be79,0x3eacbf78,
0x3f78beac,0x3e793f71,0x3f5c3edb,0xbf043f67,0xbf803e16,0xbd49bf7d,0xbf3ebf18,0x3f2cbf4e,0xbf623f22,0xbef1bf46,0xbef1bf46,0x3f62bf22,
0x3f7fbe95,0x3dc93f75,0x3dc93f75,0xbf7f3e95,0xbf75bdc9,0x3e95bf7f,0x3e95bf7f,0x3f753dc9,0x3f463ef1,0xbf223f62,0xbf223f62,0xbf46bef1,
0x3f71bf18,0x3eac3f4e,0xbedb3f7d,0xbf67be16,0xbf783d49,0x3e79bf80,0x3f5cbf3e,0x3f043f2c,0x3f2c3f04,0xbf3e3f5c,0xbf803e79,0x3d49bf78,
0xbe16bf67,0x3f7dbedb,0x3f4e3eac,0xbf183f71,0xbf7b3f0e,0xbe48bf55,0x3f7bbf0e,0x3e483f55,0x3f553e48,0xbf0e3f7b,0xbf55be48,0x3f0ebf7b,
0xbe48bf55,0x3f7bbf0e,0x3e483f55,0xbf7b3f0e,0xbf0e3f7b,0xbf55be48,0x3f0ebf7b,0x3f553e48,0x3f80bf04,0x3d493f5c,0xbf3ebe79,0x3f2cbf78,
0xbf18bedb,0x3f4ebf67,0xbe163f71,0xbf7d3eac,0xbeac3f7d,0xbf713e16,0x3f67bf4e,0x3edb3f18,0x3f78bf2c,0x3e793f3e,0xbf5cbd49,0x3f04bf80,
0xbf7f3ef1,0x3dc9bf62,0xbdc93f62,0xbf7f3ef1,0x3e953f22,0xbf753f46,0x3f75bf46,0x3e953f22,0x3f46bf75,0x3f223e95,0xbf22be95,0x3f46bf75,
0xbf623dc9,0x3ef1bf7f,0xbef13f7f,0xbf623dc9,0x3f78bedb,0xbe793f67,0x3f5cbf71,0x3f043eac,0x3d49bf4e,0x3f80bf18,0xbf2cbe16,0x3f3ebf7d,
0xbf7d3f3e,0xbe16bf2c,0xbf183f80,0xbf4e3d49,0x3eac3f04,0xbf713f5c,0x3f67be79,0xbedb3f78,0xbf6d3ec4,0x3ec4bf6d,0xbf6d3ec4,0x3ec4bf6d,
0xbec43f6d,0xbf6d3ec4,0xbec43f6d,0xbf6d3ec4,0x3f6dbec4,0xbec43f6d,0x3f6dbec4,0xbec43f6d,0x3ec4bf6d,0x3f6dbec4,0x3ec4bf6d,0x3f6dbec4,
0x3f5cbeac,0xbf043f71,0x3e793edb,0xbf783f67,0x3f2cbf7d,0x3f3ebe16,0x3f80bf4e,0x3d493f18,0xbf18bd49,0x3f4ebf80,0x3e16bf3e,0x3f7dbf2c,
0xbf673f78,0xbedbbe79,0xbf713f04,0x3eacbf5c,0xbf463e95,0x3f22bf75,0x3f22bf75,0x3f46be95,0xbf623f7f,0xbef1bdc9,0xbef1bdc9,0x3f62bf7f,
0x3dc93ef1,0xbf7f3f62,0xbf7f3f62,0xbdc9bef1,0x3f75bf22,0xbe953f46,0xbe953f46,0xbf753f22,0x3f2cbe79,0xbf3e3f78,0xbf803f5c,0x3d49bf04,
0x3f7dbf71,0x3e163eac,0xbf183f67,0xbf4e3edb,0x3edbbf4e,0x3f67bf18,0x3eac3e16,0xbf713f7d,0xbf043d49,0x3f5cbf80,0x3f78bf3e,0xbe793f2c,
0xbf0e3e48,0x3f55bf7b,0x3f0ebe48,0xbf553f7b,0xbf7b3f55,0x3e48bf0e,0x3f7bbf55,0xbe483f0e,0xbf553f7b,0xbf0e3e48,0x3f55bf7b,0x3f0ebe48,
0xbe483f0e,0xbf7b3f55,0x3e48bf0e,0x3f7bbf55,0x3edbbe16,0xbf673f7d,0x3eacbf18,0x3f71bf4e,0x3f5cbf2c,0xbf043f3e,0xbe79bd49,0x3f78bf80,
0x3f80bf78,0x3d493e79,0xbf3e3f04,0x3f2cbf5c,0x3f4ebf71,0x3f18beac,0xbf7d3f67,0x3e16bedb,0xbe953dc9,0x3f75bf7f,0xbf753f7f,0xbe953dc9,
0xbf223ef1,0x3f46bf62,0xbf463f62,0xbf223ef1,0xbf623f46,0x3ef1bf22,0xbef13f22,0xbf623f46,0xbf7f3f75,0x3dc9be95,0xbdc93e95,0xbf7f3f75,
0x3e16bd49,0xbf7d3f80,0x3f4ebf3e,0xbf183f2c,0x3eacbe79,0xbf713f78,0x3f67bf5c,0xbedb3f04,0x3f04bedb,0xbf5c3f67,0x3f78bf71,0xbe793eac,
0x3f2cbf18,0xbf3e3f4e,0x3f80bf7d,0xbd493e16,0x3f803f80,0xbf803f80,0x3f803f80,0xbf803f80,0x3f803f80,0xbf803f80,0x3f803f80,0xbf803f80,
0x3f803f80,0xbf803f80,0x3f803f80,0xbf803f80,0x3f803f80,0xbf803f80,0x3f803f80,0xbf803f80,0x3e163d49,0x3f7d3f80,0x3f4e3f3e,0x3f183f2c,
0x3eac3e79,0x3f713f78,0x3f673f5c,0x3edb3f04,0x3f043edb,0x3f5c3f67,0x3f783f71,0x3e793eac,0x3f2c3f18,0x3f3e3f4e,0x3f803f7d,0x3d493e16,
0xbf75bf7f,0x3e953dc9,0x3e953dc9,0x3f753f7f,0xbf46bf62,0x3f223ef1,0x3f223ef1,0x3f463f62,0xbef1bf22,0x3f623f46,0x3f623f46,0x3ef13f22,
0xbdc9be95,0x3f7f3f75,0x3f7f3f75,0x3dc93e95,0xbedbbe16,0xbf67bf7d,0xbeacbf18,0x3f713f4e,0xbf5cbf2c,0xbf04bf3e,0x3e79bd49,0x3f783f80,
0xbf80bf78,0x3d49be79,0x3f3e3f04,0x3f2c3f5c,0xbf4ebf71,0x3f183eac,0x3f7d3f67,0x3e163edb,0x3f553f7b,0xbf0ebe48,0xbf55bf7b,0x3f0e3e48,
0x3e483f0e,0xbf7bbf55,0xbe48bf0e,0x3f7b3f55,0xbf0ebe48,0xbf55bf7b,0x3f0e3e48,0x3f553f7b,0xbf7bbf55,0xbe48bf0e,0x3f7b3f55,0x3e483f0e,
0x3f2c3e79,0x3f3e3f78,0xbf80bf5c,0xbd49bf04,0x3f7d3f71,0xbe163eac,0xbf18bf67,0x3f4e3edb,0x3edb3f4e,0xbf67bf18,0x3eacbe16,0x3f713f7d,
0xbf04bd49,0xbf5cbf80,0x3f783f3e,0x3e793f2c,0xbf22bf75,0x3f463e95,0xbf46be95,0xbf22bf75,0x3ef1bdc9,0x3f623f7f,0xbf62bf7f,0x3ef1bdc9,
0x3f7f3f62,0xbdc93ef1,0x3dc9bef1,0x3f7f3f62,0x3e953f46,0xbf75bf22,0x3f753f22,0x3e953f46,0xbf5cbeac,0xbf04bf71,0xbe793edb,0xbf78bf67,
0xbf2cbf7d,0x3f3e3e16,0xbf80bf4e,0x3d49bf18,0x3f18bd49,0x3f4e3f80,0xbe16bf3e,0x3f7d3f2c,0x3f673f78,0xbedb3e79,0x3f713f04,0x3eac3f5c,
0x3ec43f6d,0xbf6dbec4,0x3ec43f6d,0xbf6dbec4,0xbf6dbec4,0xbec4bf6d,0xbf6dbec4,0xbec4bf6d,0xbec4bf6d,0x3f6d3ec4,0xbec4bf6d,0x3f6d3ec4,
0x3f6d3ec4,0x3ec43f6d,0x3f6d3ec4,0x3ec43f6d,0x3f783edb,0x3e793f67,0x3f5c3f71,0xbf043eac,0x3d493f4e,0xbf80bf18,0xbf2c3e16,0xbf3ebf7d,
0xbf7dbf3e,0x3e16bf2c,0xbf18bf80,0x3f4e3d49,0x3eacbf04,0x3f713f5c,0x3f673e79,0x3edb3f78,0xbdc9bf62,0x3f7f3ef1,0x3f7f3ef1,0x3dc93f62,
0x3f753f46,0xbe953f22,0xbe953f22,0xbf75bf46,0xbf223e95,0xbf46bf75,0xbf46bf75,0x3f22be95,0xbef1bf7f,0x3f623dc9,0x3f623dc9,0x3ef13f7f,
0xbf80bf04,0x3d49bf5c,0x3f3ebe79,0x3f2c3f78,0x3f18bedb,0x3f4e3f67,0x3e163f71,0xbf7dbeac,0x3eac3f7d,0xbf71be16,0xbf67bf4e,0x3edbbf18,
0xbf78bf2c,0x3e79bf3e,0x3f5cbd49,0x3f043f80,0xbe483f55,0xbf7bbf0e,0x3e48bf55,0x3f7b3f0e,0xbf0ebf7b,0x3f55be48,0x3f0e3f7b,0xbf553e48,
0x3f7b3f0e,0xbe483f55,0xbf7bbf0e,0x3e48bf55,0xbf553e48,0xbf0ebf7b,0x3f55be48,0x3f0e3f7b,0x3f713f18,0xbeac3f4e,0xbedbbf7d,0x3f67be16,
0xbf78bd49,0xbe79bf80,0x3f5c3f3e,0xbf043f2c,0x3f2cbf04,0x3f3e3f5c,0xbf80be79,0xbd49bf78,0xbe163f67,0xbf7dbedb,0x3f4ebeac,0x3f183f71,
0x3ef1bf46,0x3f623f22,0xbf62bf22,0x3ef1bf46,0xbdc93f75,0xbf7fbe95,0x3f7f3e95,0xbdc93f75,0xbe95bf7f,0x3f75bdc9,0xbf753dc9,0xbe95bf7f,
0x3f223f62,0xbf463ef1,0x3f46bef1,0x3f223f62,0xbf4ebf2c,0x3f18bf3e,0xbf7d3d49,0xbe16bf80,0x3f673f04,0xbedb3f5c,0x3f71be79,0x3eac3f78,
0xbf78beac,0x3e79bf71,0xbf5c3edb,0xbf04bf67,0x3f803e16,0xbd493f7d,0x3f3ebf18,0x3f2c3f4e,0xbf353f35,0xbf35bf35,0xbf353f35,0xbf35bf35,
0x3f35bf35,0x3f353f35,0x3f35bf35,0x3f353f35,0xbf353f35,0xbf35bf35,0xbf353f35,0xbf35bf35,0x3f35bf35,0x3f353f35,0x3f35bf35,0x3f353f35,
0x3f183f3e,0xbf4e3f2c,0xbe163f80,0xbf7dbd49,0xbedbbf5c,0x3f67bf04,0x3eacbf78,0x3f713e79,0x3e793f71,0xbf783eac,0xbf043f67,0xbf5cbedb,
0xbd49bf7d,0x3f80be16,0x3f2cbf4e,0x3f3e3f18,0x3f62bf22,0x3ef13f46,0x3ef13f46,0xbf623f22,0xbf7f3e95,0xbdc9bf75,0xbdc9bf75,0x3f7fbe95,
0x3f753dc9,0xbe953f7f,0xbe953f7f,0xbf75bdc9,0xbf46bef1,0x3f22bf62,0x3f22bf62,0x3f463ef1,0xbeacbf4e,0x3f71bf18,0x3f673e16,0xbedb3f7d,
0xbe793f80,0xbf783d49,0xbf04bf2c,0x3f5cbf3e,0x3f3ebf5c,0x3f2c3f04,0xbd493f78,0xbf803e79,0xbf7d3edb,0xbe16bf67,0x3f18bf71,0x3f4e3eac,
0xbf7b3f0e,0xbe48bf55,0x3f7bbf0e,0x3e483f55,0x3f553e48,0xbf0e3f7b,0xbf55be48,0x3f0ebf7b,0xbe48bf55,0x3f7bbf0e,0x3e483f55,0xbf7b3f0e,
0xbf0e3f7b,0xbf55be48,0x3f0ebf7b,0x3f553e48,0x3d493f5c,0xbf803f04,0x3f2cbf78,0x3f3e3e79,0x3f4ebf67,0x3f183edb,0xbf7d3eac,0x3e16bf71,
0xbf713e16,0x3eacbf7d,0x3edb3f18,0xbf673f4e,0x3e793f3e,0xbf783f2c,0x3f04bf80,0x3f5c3d49,0x3f7fbef1,0xbdc93f62,0x3dc9bf62,0x3f7fbef1,
0xbe95bf22,0x3f75bf46,0xbf753f46,0xbe95bf22,0xbf463f75,0xbf22be95,0x3f223e95,0xbf463f75,0x3f62bdc9,0xbef13f7f,0x3ef1bf7f,0x3f62bdc9,
0x3e79bf67,0x3f78bedb,0xbf04beac,0x3f5cbf71,0xbf803f18,0x3d49bf4e,0xbf3e3f7d,0xbf2cbe16,0x3e163f2c,0xbf7d3f3e,0x3f4ebd49,0xbf183f80,
0x3f71bf5c,0x3eac3f04,0x3edbbf78,0x3f67be79,0xbf6d3ec4,0x3ec4bf6d,0xbf6d3ec4,0x3ec4bf6d,0xbec43f6d,0xbf6d3ec4,0xbec43f6d,0xbf6d3ec4,
0x3f6dbec4,0xbec43f6d,0x3f6dbec4,0xbec43f6d,0x3ec4bf6d,0x3f6dbec4,0x3ec4bf6d,0x3f6dbec4,0xbf043f71,0xbf5c3eac,0xbf783f67,0xbe79bedb,
0x3f3ebe16,0xbf2c3f7d,0x3d493f18,0xbf803f4e,0x3f4ebf80,0x3f183d49,0x3f7dbf2c,0xbe163f3e,0xbedbbe79,0x3f67bf78,0x3eacbf5c,0x3f71bf04,
0x3f46be95,0xbf223f75,0xbf223f75,0xbf463e95,0x3f62bf7f,0x3ef13dc9,0x3ef13dc9,0xbf623f7f,0xbdc9bef1,0x3f7fbf62,0x3f7fbf62,0x3dc93ef1,
0xbf753f22,0x3e95bf46,0x3e95bf46,0x3f75bf22,0x3f3ebf78,0x3f2cbe79,0xbd493f04,0xbf803f5c,0xbe16beac,0x3f7dbf71,0x3f4ebedb,0xbf183f67,
0xbf673f18,0x3edbbf4e,0x3f71bf7d,0x3eac3e16,0xbf5c3f80,0xbf043d49,0x3e79bf2c,0x3f78bf3e,0xbf0e3e48,0x3f55bf7b,0x3f0ebe48,0xbf553f7b,
0xbf7b3f55,0x3e48bf0e,0x3f7bbf55,0xbe483f0e,0xbf553f7b,0xbf0e3e48,0x3f55bf7b,0x3f0ebe48,0xbe483f0e,0xbf7b3f55,0x3e48bf0e,0x3f7bbf55,
0xbf673f7d,0xbedb3e16,0x3f71bf4e,0xbeac3f18,0xbf043f3e,0xbf5c3f2c,0x3f78bf80,0x3e793d49,0x3d493e79,0xbf803f78,0x3f2cbf5c,0x3f3ebf04,
0x3f18beac,0xbf4e3f71,0x3e16bedb,0x3f7dbf67,0x3e95bdc9,0xbf753f7f,0x3f75bf7f,0x3e95bdc9,0x3f22bef1,0xbf463f62,0x3f46bf62,0x3f22bef1,
0x3f62bf46,0xbef13f22,0x3ef1bf22,0x3f62bf46,0x3f7fbf75,0xbdc93e95,0x3dc9be95,0x3f7fbf75,0x3f7dbf80,0x3e16bd49,0x3f18bf2c,0x3f4ebf3e,
0x3f71bf78,0x3eacbe79,0x3edbbf04,0x3f67bf5c,0x3f5cbf67,0x3f04bedb,0x3e79beac,0x3f78bf71,0x3f3ebf4e,0x3f2cbf18,0x3d49be16,0x3f80bf7d,
0x3f803f80,0xbf353f35,0x3f803f80,0xbf353f35,0x3f803f80,0xbf353f35,0x3f803f80,0xbf353f35,0x3f803f80,0xbf353f35,0x3f803f80,0xbf353f35,
0x3f803f80,0xbf353f35,0x3f803f80,0xbf353f35,0x3f7c3f7f,0xbe2fbd97,0x3f133f27,0xbf51bf42,0x3f6f3f77,0xbeb8be89,0x3ecf3efc,0xbf6abf5f,
0x3f583f65,0xbf09bee6,0x3e603ea1,0xbf7abf73,0x3f393f4a,0xbf31bf1d,0x3cc93dfb,0xbf80bf7e,0x3f713f7d,0xbeacbe16,0xbeacbe16,0xbf71bf7d,
0x3f3e3f5c,0xbf2cbf04,0xbf2cbf04,0xbf3ebf5c,0x3edb3f18,0xbf67bf4e,0xbf67bf4e,0xbedbbf18,0x3d493e79,0xbf80bf78,0xbf80bf78,0xbd49be79,
0x3f5f3f7a,0xbefcbe60,0xbf77bf58,0xbe89bf09,0x3ee63f31,0xbf65bf39,0xbf73bf80,0x3ea13cc9,0xbdfb3e2f,0xbf7ebf7c,0xbf1dbf51,0x3f4a3f13,
0xbf27becf,0xbf42bf6a,0xbd97beb8,0x3f7f3f6f,0x3f463f75,0xbf22be95,0xbf46bf75,0x3f223e95,0x3dc93ef1,0xbf7fbf62,0xbdc9bef1,0x3f7f3f62,
0xbf22be95,0xbf46bf75,0x3f223e95,0x3f463f75,0xbf7fbf62,0xbdc9bef1,0x3f7f3f62,0x3dc93ef1,0x3f273f6f,0xbf42beb8,0x3d97becf,0x3f7f3f6a,
0xbe893e60,0xbf77bf7a,0x3f5f3f09,0x3efc3f58,0xbf73bf31,0xbea1bf39,0x3f653f80,0xbee63cc9,0xbf4abf7c,0x3f1d3e2f,0x3dfb3f13,0xbf7ebf51,
0x3f043f67,0xbf5cbedb,0x3f5c3edb,0x3f043f67,0xbf18bd49,0xbf4ebf80,0x3f4e3f80,0xbf18bd49,0xbf78bf71,0x3e79beac,0xbe793eac,0xbf78bf71,
0xbe16bf2c,0x3f7d3f3e,0xbf7dbf3e,0xbe16bf2c,0x3eb83f5f,0xbf6fbefc,0x3f6a3f77,0xbecf3e89,0xbf58bea1,0xbf09bf73,0xbe603ee6,0xbf7abf65,
0xbf31bf7e,0x3f393dfb,0xbf80bf4a,0x3cc9bf1d,0x3f13bd97,0x3f513f7f,0xbe2fbf42,0x3f7c3f27,0x3e483f55,0xbf7bbf0e,0x3e483f55,0xbf7bbf0e,
0xbf7bbf0e,0xbe48bf55,0xbf7bbf0e,0xbe48bf55,0xbe48bf55,0x3f7b3f0e,0xbe48bf55,0x3f7b3f0e,0x3f7b3f0e,0x3e483f55,0x3f7b3f0e,0x3e483f55,
0x3cc93f4a,0xbf80bf1d,0xbf313dfb,0xbf39bf7e,0xbf7cbf42,0x3e2fbf27,0xbf13bf7f,0x3f513d97,0x3eb8befc,0x3f6f3f5f,0x3f6a3e89,0x3ecf3f77,
0x3f583f73,0xbf093ea1,0x3e603f65,0xbf7abee6,0xbe163f3e,0xbf7dbf2c,0xbf7dbf2c,0x3e16bf3e,0xbf5cbf67,0x3f04bedb,0x3f04bedb,0x3f5c3f67,
0x3f4ebd49,0x3f183f80,0x3f183f80,0xbf4e3d49,0x3e793f71,0xbf78beac,0xbf78beac,0xbe79bf71,0xbea13f31,0xbf73bf39,0xbee6bf80,0x3f653cc9,
0xbf1dbf7c,0x3f4abe2f,0x3f7e3f13,0xbdfb3f51,0x3f7f3ecf,0x3d973f6a,0xbf273eb8,0xbf42bf6f,0xbefc3f09,0xbf5fbf58,0xbe89bf7a,0x3f773e60,
0xbef13f22,0xbf62bf46,0x3ef1bf22,0x3f623f46,0xbe95bf7f,0x3f753dc9,0x3e953f7f,0xbf75bdc9,0x3f623f46,0xbef13f22,0xbf62bf46,0x3ef1bf22,
0xbf75bdc9,0xbe95bf7f,0x3f753dc9,0x3e953f7f,0xbf1d3f13,0xbf4abf51,0x3f7e3e2f,0x3dfb3f7c,0x3d97bf6f,0x3f7f3eb8,0xbf423ecf,0xbf27bf6a,
0x3efc3f7a,0xbf5f3e60,0x3e89bf58,0x3f773f09,0xbf65bf31,0x3ee6bf39,0x3ea13f80,0xbf733cc9,0xbf3e3f04,0xbf2cbf5c,0x3f2c3f5c,0xbf3e3f04,
0x3edbbf4e,0x3f673f18,0xbf67bf18,0x3edbbf4e,0xbd493f78,0xbf80be79,0x3f803e79,0xbd493f78,0xbeacbf7d,0x3f71be16,0xbf713e16,0xbeacbf7d,
0xbf583ee6,0xbf09bf65,0xbe603f73,0xbf7abea1,0x3f39bf1d,0x3f313f4a,0x3cc9bf7e,0x3f803dfb,0xbf133f42,0xbf51bf27,0x3e2f3f7f,0xbf7c3d97,
0x3ecfbf5f,0x3f6a3efc,0xbeb8bf77,0x3f6fbe89,0xbf6d3ec4,0xbec4bf6d,0xbf6d3ec4,0xbec4bf6d,0x3f6dbec4,0x3ec43f6d,0x3f6dbec4,0x3ec43f6d,
0xbf6d3ec4,0xbec4bf6d,0xbf6d3ec4,0xbec4bf6d,0x3f6dbec4,0x3ec43f6d,0x3f6dbec4,0x3ec43f6d,0xbf7a3ea1,0xbe60bf73,0xbf58bee6,0x3f09bf65,
0x3f80bdfb,0x3cc93f7e,0x3f393f1d,0xbf313f4a,0xbf7cbd97,0x3e2fbf7f,0xbf13bf42,0x3f51bf27,0x3f6f3e89,0xbeb83f77,0x3ecf3f5f,0xbf6a3efc,
0xbf803e79,0xbd49bf78,0xbd49bf78,0x3f80be79,0x3f713e16,0xbeac3f7d,0xbeac3f7d,0xbf71be16,0xbf3ebf04,0x3f2cbf5c,0x3f2cbf5c,0x3f3e3f04,
0x3edb3f4e,0xbf673f18,0xbf673f18,0xbedbbf4e,0xbf7e3e2f,0x3dfbbf7c,0x3f4abf51,0x3f1d3f13,0x3f423ecf,0xbf273f6a,0xbf7f3eb8,0xbd97bf6f,
0xbe89bf58,0x3f77bf09,0x3f5f3e60,0xbefc3f7a,0xbea13f80,0xbf73bcc9,0xbee6bf39,0x3f65bf31,0xbf753dc9,0x3e95bf7f,0x3f75bdc9,0xbe953f7f,
0x3ef13f22,0xbf623f46,0xbef1bf22,0x3f62bf46,0x3e95bf7f,0x3f75bdc9,0xbe953f7f,0xbf753dc9,0xbf623f46,0xbef1bf22,0x3f62bf46,0x3ef13f22,
0xbf653cc9,0x3ee6bf80,0x3ea13f31,0xbf733f39,0x3dfb3f51,0xbf7e3f13,0x3f1dbf7c,0x3f4a3e2f,0x3f42bf6f,0x3f273eb8,0xbf7f3ecf,0x3d97bf6a,
0xbf773e60,0x3e89bf7a,0x3efc3f09,0xbf5f3f58,0xbf4ebd49,0x3f18bf80,0xbf183f80,0xbf4ebd49,0xbe793f71,0xbf783eac,0x3f78beac,0xbe793f71,
0x3f7dbf2c,0x3e163f3e,0xbe16bf3e,0x3f7dbf2c,0xbf04bedb,0x3f5cbf67,0xbf5c3f67,0xbf04bedb,0xbf31bdfb,0x3f39bf7e,0xbf803f1d,0x3cc9bf4a,
0xbf133f7f,0xbf513d97,0x3e2f3f27,0xbf7c3f42,0x3f6abe89,0xbecf3f77,0x3f6fbf5f,0x3eb83efc,0x3e60bf65,0x3f7abee6,0xbf09bea1,0x3f58bf73,
0xbf0ebe48,0x3f55bf7b,0xbf0ebe48,0x3f55bf7b,0xbf553f7b,0xbf0ebe48,0xbf553f7b,0xbf0ebe48,0x3f0e3e48,0xbf553f7b,0x3f0e3e48,0xbf553f7b,
0x3f55bf7b,0x3f0e3e48,0x3f55bf7b,0x3f0e3e48,0xbecfbe89,0x3f6abf77,0x3eb8bf5f,0x3f6fbefc,0xbf7a3f65,0xbe60bee6,0xbf583ea1,0x3f09bf73,
0x3cc93f1d,0xbf803f4a,0xbf313f7e,0xbf393dfb,0x3f7cbf27,0xbe2f3f42,0x3f133d97,0xbf513f7f,0xbe79beac,0x3f78bf71,0x3f78bf71,0x3e793eac,
0xbf7d3f3e,0x3e16bf2c,0x3e16bf2c,0x3f7dbf3e,0xbf043f67,0xbf5c3edb,0xbf5c3edb,0x3f04bf67,0x3f18bd49,0xbf4e3f80,0xbf4e3f80,0xbf183d49,
0xbd97becf,0x3f7fbf6a,0x3f42beb8,0xbf273f6f,0xbf5f3f09,0x3efcbf58,0x3f77bf7a,0x3e893e60,0xbf653f80,0xbee6bcc9,0x3ea1bf39,0x3f73bf31,
0xbdfb3f13,0xbf7e3f51,0xbf1d3e2f,0x3f4abf7c,0x3dc9bef1,0x3f7fbf62,0xbdc93ef1,0xbf7f3f62,0xbf223e95,0x3f46bf75,0x3f22be95,0xbf463f75,
0xbf7f3f62,0x3dc9bef1,0x3f7fbf62,0xbdc93ef1,0xbf463f75,0xbf223e95,0x3f46bf75,0x3f22be95,0x3e89bf09,0x3f77bf58,0xbf5f3f7a,0xbefc3e60,
0xbea13cc9,0x3f73bf80,0xbee63f31,0xbf653f39,0xbf4a3f13,0x3f1dbf51,0x3dfb3e2f,0xbf7e3f7c,0xbf7f3f6f,0x3d97beb8,0x3f27becf,0xbf423f6a,
0x3edbbf18,0x3f67bf4e,0xbf673f4e,0x3edbbf18,0x3d49be79,0x3f80bf78,0xbf803f78,0x3d49be79,0xbeac3e16,0x3f71bf7d,0xbf713f7d,0xbeac3e16,
0xbf2c3f04,0x3f3ebf5c,0xbf3e3f5c,0xbf2c3f04,0x3f13bf27,0x3f51bf42,0xbe2f3d97,0x3f7cbf7f,0x3ecfbefc,0x3f6abf5f,0xbeb83e89,0x3f6fbf77,
0x3e60bea1,0x3f7abf73,0xbf093ee6,0x3f58bf65,0x3cc9bdfb,0x3f80bf7e,0xbf313f1d,0x3f39bf4a,0x3f803f80,0xbf353f35,0x3f803f80,0xbf353f35,
0x3f803f80,0xbf353f35,0x3f803f80,0xbf353f35,0x3f803f80,0xbf353f35,0x3f803f80,0xbf353f35,0x3f803f80,0xbf353f35,0x3f803f80,0xbf353f35,
0xbe2fbd97,0xbf7cbf7f,0xbf51bf42,0xbf13bf27,0xbeb8be89,0xbf6fbf77,0xbf6abf5f,0xbecfbefc,0xbf09bee6,0xbf58bf65,0xbf7abf73,0xbe60bea1,
0xbf31bf1d,0xbf39bf4a,0xbf80bf7e,0xbcc9bdfb,0xbf71bf7d,0x3eac3e16,0x3eac3e16,0x3f713f7d,0xbf3ebf5c,0x3f2c3f04,0x3f2c3f04,0x3f3e3f5c,
0xbedbbf18,0x3f673f4e,0x3f673f4e,0x3edb3f18,0xbd49be79,0x3f803f78,0x3f803f78,0x3d493e79,0x3efc3e60,0x3f5f3f7a,0x3e893f09,0xbf77bf58,
0x3f653f39,0x3ee63f31,0xbea1bcc9,0xbf73bf80,0x3f7e3f7c,0xbdfb3e2f,0xbf4abf13,0xbf1dbf51,0x3f423f6a,0xbf27becf,0xbf7fbf6f,0xbd97beb8,
0x3f463f75,0xbf22be95,0xbf46bf75,0x3f223e95,0x3dc93ef1,0xbf7fbf62,0xbdc9bef1,0x3f7f3f62,0xbf22be95,0xbf46bf75,0x3f223e95,0x3f463f75,
0xbf7fbf62,0xbdc9bef1,0x3f7f3f62,0x3dc93ef1,0xbf42beb8,0xbf27bf6f,0x3f7f3f6a,0xbd973ecf,0xbf77bf7a,0x3e89be60,0x3efc3f58,0xbf5fbf09,
0xbea1bf39,0x3f733f31,0xbee63cc9,0xbf65bf80,0x3f1d3e2f,0x3f4a3f7c,0xbf7ebf51,0xbdfbbf13,0xbf04bf67,0x3f5c3edb,0xbf5cbedb,0xbf04bf67,
0x3f183d49,0x3f4e3f80,0xbf4ebf80,0x3f183d49,0x3f783f71,0xbe793eac,0x3e79beac,0x3f783f71,0x3e163f2c,0xbf7dbf3e,0x3f7d3f3e,0x3e163f2c,
0x3f6f3efc,0x3eb83f5f,0x3ecfbe89,0x3f6a3f77,0x3f093f73,0xbf58bea1,0x3f7a3f65,0xbe603ee6,0xbf39bdfb,0xbf31bf7e,0xbcc93f1d,0xbf80bf4a,
0xbf51bf7f,0x3f13bd97,0xbf7cbf27,0xbe2fbf42,0x3e483f55,0xbf7bbf0e,0x3e483f55,0xbf7bbf0e,0xbf7bbf0e,0xbe48bf55,0xbf7bbf0e,0xbe48bf55,
0xbe48bf55,0x3f7b3f0e,0xbe48bf55,0x3f7b3f0e,0x3f7b3f0e,0x3e483f55,0x3f7b3f0e,0x3e483f55,0xbf80bf1d,0xbcc9bf4a,0xbf39bf7e,0x3f31bdfb,
0x3e2fbf27,0x3f7c3f42,0x3f513d97,0x3f133f7f,0x3f6f3f5f,0xbeb83efc,0x3ecf3f77,0xbf6abe89,0xbf093ea1,0xbf58bf73,0xbf7abee6,0xbe60bf65,
0x3e16bf3e,0x3f7d3f2c,0x3f7d3f2c,0xbe163f3e,0x3f5c3f67,0xbf043edb,0xbf043edb,0xbf5cbf67,0xbf4e3d49,0xbf18bf80,0xbf18bf80,0x3f4ebd49,
0xbe79bf71,0x3f783eac,0x3f783eac,0x3e793f71,0x3f733f39,0xbea13f31,0xbf65bcc9,0xbee6bf80,0xbf4a3e2f,0xbf1dbf7c,0x3dfbbf51,0x3f7e3f13,
0xbd97bf6a,0x3f7f3ecf,0x3f423f6f,0xbf273eb8,0x3f5f3f58,0xbefc3f09,0xbf77be60,0xbe89bf7a,0xbef13f22,0xbf62bf46,0x3ef1bf22,0x3f623f46,
0xbe95bf7f,0x3f753dc9,0x3e953f7f,0xbf75bdc9,0x3f623f46,0xbef13f22,0xbf62bf46,0x3ef1bf22,0xbf75bdc9,0xbe95bf7f,0x3f753dc9,0x3e953f7f,
0xbf4abf51,0x3f1dbf13,0x3dfb3f7c,0xbf7ebe2f,0x3f7f3eb8,0xbd973f6f,0xbf27bf6a,0x3f42becf,0xbf5f3e60,0xbefcbf7a,0x3f773f09,0xbe893f58,
0x3ee6bf39,0x3f653f31,0xbf733cc9,0xbea1bf80,0x3f3ebf04,0x3f2c3f5c,0xbf2cbf5c,0x3f3ebf04,0xbedb3f4e,0xbf67bf18,0x3f673f18,0xbedb3f4e,
0x3d49bf78,0x3f803e79,0xbf80be79,0x3d49bf78,0x3eac3f7d,0xbf713e16,0x3f71be16,0x3eac3f7d,0x3f093f65,0xbf583ee6,0x3f7a3ea1,0xbe603f73,
0xbf31bf4a,0x3f39bf1d,0xbf80bdfb,0x3cc9bf7e,0x3f513f27,0xbf133f42,0x3f7cbd97,0x3e2f3f7f,0xbf6abefc,0x3ecfbf5f,0xbf6f3e89,0xbeb8bf77,
0xbf6d3ec4,0xbec4bf6d,0xbf6d3ec4,0xbec4bf6d,0x3f6dbec4,0x3ec43f6d,0x3f6dbec4,0x3ec43f6d,0xbf6d3ec4,0xbec4bf6d,0xbf6d3ec4,0xbec4bf6d,
0x3f6dbec4,0x3ec43f6d,0x3f6dbec4,0x3ec43f6d,0xbe60bf73,0x3f7abea1,0x3f09bf65,0x3f583ee6,0x3cc93f7e,0xbf803dfb,0xbf313f4a,0xbf39bf1d,
0x3e2fbf7f,0x3f7c3d97,0x3f51bf27,0x3f133f42,0xbeb83f77,0xbf6fbe89,0xbf6a3efc,0xbecfbf5f,0x3f80be79,0x3d493f78,0x3d493f78,0xbf803e79,
0xbf71be16,0x3eacbf7d,0x3eacbf7d,0x3f713e16,0x3f3e3f04,0xbf2c3f5c,0xbf2c3f5c,0xbf3ebf04,0xbedbbf4e,0x3f67bf18,0x3f67bf18,0x3edb3f4e,
0xbdfb3f7c,0xbf7e3e2f,0xbf1dbf13,0x3f4abf51,0x3f27bf6a,0x3f423ecf,0x3d973f6f,0xbf7f3eb8,0xbf773f09,0xbe89bf58,0x3efcbf7a,0x3f5f3e60,
0x3f733cc9,0xbea13f80,0xbf653f31,0xbee6bf39,0xbf753dc9,0x3e95bf7f,0x3f75bdc9,0xbe953f7f,0x3ef13f22,0xbf623f46,0xbef1bf22,0x3f62bf46,
0x3e95bf7f,0x3f75bdc9,0xbe953f7f,0xbf753dc9,0xbf623f46,0xbef1bf22,0x3f62bf46,0x3ef13f22,0x3ee6bf80,0x3f65bcc9,0xbf733f39,0xbea1bf31,
0xbf7e3f13,0xbdfbbf51,0x3f4a3e2f,0xbf1d3f7c,0x3f273eb8,0xbf423f6f,0x3d97bf6a,0x3f7fbecf,0x3e89bf7a,0x3f77be60,0xbf5f3f58,0xbefcbf09,
0x3f4e3d49,0xbf183f80,0x3f18bf80,0x3f4e3d49,0x3e79bf71,0x3f78beac,0xbf783eac,0x3e79bf71,0xbf7d3f2c,0xbe16bf3e,0x3e163f3e,0xbf7d3f2c,
0x3f043edb,0xbf5c3f67,0x3f5cbf67,0x3f043edb,0xbf393f7e,0xbf31bdfb,0xbcc93f4a,0xbf803f1d,0x3f51bd97,0xbf133f7f,0x3f7cbf42,0x3e2f3f27,
0x3ecfbf77,0x3f6abe89,0xbeb8befc,0x3f6fbf5f,0xbf7a3ee6,0x3e60bf65,0xbf583f73,0xbf09bea1,0xbf0ebe48,0x3f55bf7b,0xbf0ebe48,0x3f55bf7b,
0xbf553f7b,0xbf0ebe48,0xbf553f7b,0xbf0ebe48,0x3f0e3e48,0xbf553f7b,0x3f0e3e48,0xbf553f7b,0x3f55bf7b,0x3f0e3e48,0x3f55bf7b,0x3f0e3e48,
0x3f6abf77,0x3ecf3e89,0x3f6fbefc,0xbeb83f5f,0xbe60bee6,0x3f7abf65,0x3f09bf73,0x3f58bea1,0xbf803f4a,0xbcc9bf1d,0xbf393dfb,0x3f31bf7e,
0xbe2f3f42,0xbf7c3f27,0xbf513f7f,0xbf13bd97,0x3e793eac,0xbf783f71,0xbf783f71,0xbe79beac,0x3f7dbf3e,0xbe163f2c,0xbe163f2c,0xbf7d3f3e,
0x3f04bf67,0x3f5cbedb,0x3f5cbedb,0xbf043f67,0xbf183d49,0x3f4ebf80,0x3f4ebf80,0x3f18bd49,0xbf7f3f6a,0xbd97becf,0x3f27bf6f,0x3f42beb8,
0xbefc3f58,0xbf5f3f09,0xbe89be60,0x3f77bf7a,0x3ee63cc9,0xbf653f80,0xbf733f31,0x3ea1bf39,0x3f7ebf51,0xbdfb3f13,0xbf4a3f7c,0xbf1d3e2f,
0x3dc9bef1,0x3f7fbf62,0xbdc93ef1,0xbf7f3f62,0xbf223e95,0x3f46bf75,0x3f22be95,0xbf463f75,0xbf7f3f62,0x3dc9bef1,0x3f7fbf62,0xbdc93ef1,
0xbf463f75,0xbf223e95,0x3f46bf75,0x3f22be95,0x3f77bf58,0xbe893f09,0xbefc3e60,0x3f5fbf7a,0x3f73bf80,0x3ea1bcc9,0xbf653f39,0x3ee6bf31,
0x3f1dbf51,0x3f4abf13,0xbf7e3f7c,0xbdfbbe2f,0x3d97beb8,0x3f7fbf6f,0xbf423f6a,0xbf273ecf,0xbedb3f18,0xbf673f4e,0x3f67bf4e,0xbedb3f18,
0xbd493e79,0xbf803f78,0x3f80bf78,0xbd493e79,0x3eacbe16,0xbf713f7d,0x3f71bf7d,0x3eacbe16,0x3f2cbf04,0xbf3e3f5c,0x3f3ebf5c,0x3f2cbf04,
0xbf513f42,0x3f13bf27,0xbf7c3f7f,0xbe2f3d97,0xbf6a3f5f,0x3ecfbefc,0xbf6f3f77,0xbeb83e89,0xbf7a3f73,0x3e60bea1,0xbf583f65,0xbf093ee6,
0xbf803f7e,0x3cc9bdfb,0xbf393f4a,0xbf313f1d,0x3f803f80,0xbf353f35,0x3f803f80,0xbf353f35,0x3f803f80,0xbf353f35,0x3f803f80,0xbf353f35,
0x3f803f80,0xbf353f35,0x3f803f80,0xbf353f35,0x3f803f80,0xbf353f35,0x3f803f80,0xbf353f35,0xbf7cbf7f,0x3e2f3d97,0xbf13bf27,0x3f513f42,
0xbf6fbf77,0x3eb83e89,0xbecfbefc,0x3f6a3f5f,0xbf58bf65,0x3f093ee6,0xbe60bea1,0x3f7a3f73,0xbf39bf4a,0x3f313f1d,0xbcc9bdfb,0x3f803f7e,
0x3f713f7d,0xbeacbe16,0xbeacbe16,0xbf71bf7d,0x3f3e3f5c,0xbf2cbf04,0xbf2cbf04,0xbf3ebf5c,0x3edb3f18,0xbf67bf4e,0xbf67bf4e,0xbedbbf18,
0x3d493e79,0xbf80bf78,0xbf80bf78,0xbd49be79,0xbf5fbf7a,0x3efc3e60,0x3f773f58,0x3e893f09,0xbee6bf31,0x3f653f39,0x3f733f80,0xbea1bcc9,
0x3dfbbe2f,0x3f7e3f7c,0x3f1d3f51,0xbf4abf13,0x3f273ecf,0x3f423f6a,0x3d973eb8,0xbf7fbf6f,0x3f463f75,0xbf22be95,0xbf46bf75,0x3f223e95,
0x3dc93ef1,0xbf7fbf62,0xbdc9bef1,0x3f7f3f62,0xbf22be95,0xbf46bf75,0x3f223e95,0x3f463f75,0xbf7fbf62,0xbdc9bef1,0x3f7f3f62,0x3dc93ef1,
0xbf27bf6f,0x3f423eb8,0xbd973ecf,0xbf7fbf6a,0x3e89be60,0x3f773f7a,0xbf5fbf09,0xbefcbf58,0x3f733f31,0x3ea13f39,0xbf65bf80,0x3ee6bcc9,
0x3f4a3f7c,0xbf1dbe2f,0xbdfbbf13,0x3f7e3f51,0x3f043f67,0xbf5cbedb,0x3f5c3edb,0x3f043f67,0xbf18bd49,0xbf4ebf80,0x3f4e3f80,0xbf18bd49,
0xbf78bf71,0x3e79beac,0xbe793eac,0xbf78bf71,0xbe16bf2c,0x3f7d3f3e,0xbf7dbf3e,0xbe16bf2c,0xbeb8bf5f,0x3f6f3efc,0xbf6abf77,0x3ecfbe89,
0x3f583ea1,0x3f093f73,0x3e60bee6,0x3f7a3f65,0x3f313f7e,0xbf39bdfb,0x3f803f4a,0xbcc93f1d,0xbf133d97,0xbf51bf7f,0x3e2f3f42,0xbf7cbf27,
0x3e483f55,0xbf7bbf0e,0x3e483f55,0xbf7bbf0e,0xbf7bbf0e,0xbe48bf55,0xbf7bbf0e,0xbe48bf55,0xbe48bf55,0x3f7b3f0e,0xbe48bf55,0x3f7b3f0e,
0x3f7b3f0e,0x3e483f55,0x3f7b3f0e,0x3e483f55,0xbcc9bf4a,0x3f803f1d,0x3f31bdfb,0x3f393f7e,0x3f7c3f42,0xbe2f3f27,0x3f133f7f,0xbf51bd97,
0xbeb83efc,0xbf6fbf5f,0xbf6abe89,0xbecfbf77,0xbf58bf73,0x3f09bea1,0xbe60bf65,0x3f7a3ee6,0xbe163f3e,0xbf7dbf2c,0xbf7dbf2c,0x3e16bf3e,
0xbf5cbf67,0x3f04bedb,0x3f04bedb,0x3f5c3f67,0x3f4ebd49,0x3f183f80,0x3f183f80,0xbf4e3d49,0x3e793f71,0xbf78beac,0xbf78beac,0xbe79bf71,
0x3ea1bf31,0x3f733f39,0x3ee63f80,0xbf65bcc9,0x3f1d3f7c,0xbf4a3e2f,0xbf7ebf13,0x3dfbbf51,0xbf7fbecf,0xbd97bf6a,0x3f27beb8,0x3f423f6f,
0x3efcbf09,0x3f5f3f58,0x3e893f7a,0xbf77be60,0xbef13f22,0xbf62bf46,0x3ef1bf22,0x3f623f46,0xbe95bf7f,0x3f753dc9,0x3e953f7f,0xbf75bdc9,
0x3f623f46,0xbef13f22,0xbf62bf46,0x3ef1bf22,0xbf75bdc9,0xbe95bf7f,0x3f753dc9,0x3e953f7f,0x3f1dbf13,0x3f4a3f51,0xbf7ebe2f,0xbdfbbf7c,
0xbd973f6f,0xbf7fbeb8,0x3f42becf,0x3f273f6a,0xbefcbf7a,0x3f5fbe60,0xbe893f58,0xbf77bf09,0x3f653f31,0xbee63f39,0xbea1bf80,0x3f73bcc9,
0xbf3e3f04,0xbf2cbf5c,0x3f2c3f5c,0xbf3e3f04,0x3edbbf4e,0x3f673f18,0xbf67bf18,0x3edbbf4e,0xbd493f78,0xbf80be79,0x3f803e79,0xbd493f78,
0xbeacbf7d,0x3f71be16,0xbf713e16,0xbeacbf7d,0x3f58bee6,0x3f093f65,0x3e60bf73,0x3f7a3ea1,0xbf393f1d,0xbf31bf4a,0xbcc93f7e,0xbf80bdfb,
0x3f13bf42,0x3f513f27,0xbe2fbf7f,0x3f7cbd97,0xbecf3f5f,0xbf6abefc,0x3eb83f77,0xbf6f3e89,0xbf6d3ec4,0xbec4bf6d,0xbf6d3ec4,0xbec4bf6d,
0x3f6dbec4,0x3ec43f6d,0x3f6dbec4,0x3ec43f6d,0xbf6d3ec4,0xbec4bf6d,0xbf6d3ec4,0xbec4bf6d,0x3f6dbec4,0x3ec43f6d,0x3f6dbec4,0x3ec43f6d,
0x3f7abea1,0x3e603f73,0x3f583ee6,0xbf093f65,0xbf803dfb,0xbcc9bf7e,0xbf39bf1d,0x3f31bf4a,0x3f7c3d97,0xbe2f3f7f,0x3f133f42,0xbf513f27,
0xbf6fbe89,0x3eb8bf77,0xbecfbf5f,0x3f6abefc,0xbf803e79,0xbd49bf78,0xbd49bf78,0x3f80be79,0x3f713e16,0xbeac3f7d,0xbeac3f7d,0xbf71be16,
0xbf3ebf04,0x3f2cbf5c,0x3f2cbf5c,0x3f3e3f04,0x3edb3f4e,0xbf673f18,0xbf673f18,0xbedbbf4e,0x3f7ebe2f,0xbdfb3f7c,0xbf4a3f51,0xbf1dbf13,
0xbf42becf,0x3f27bf6a,0x3f7fbeb8,0x3d973f6f,0x3e893f58,0xbf773f09,0xbf5fbe60,0x3efcbf7a,0x3ea1bf80,0x3f733cc9,0x3ee63f39,0xbf653f31,
0xbf753dc9,0x3e95bf7f,0x3f75bdc9,0xbe953f7f,0x3ef13f22,0xbf623f46,0xbef1bf22,0x3f62bf46,0x3e95bf7f,0x3f75bdc9,0xbe953f7f,0xbf753dc9,
0xbf623f46,0xbef1bf22,0x3f62bf46,0x3ef13f22,0x3f65bcc9,0xbee63f80,0xbea1bf31,0x3f73bf39,0xbdfbbf51,0x3f7ebf13,0xbf1d3f7c,0xbf4abe2f,
0xbf423f6f,0xbf27beb8,0x3f7fbecf,0xbd973f6a,0x3f77be60,0xbe893f7a,0xbefcbf09,0x3f5fbf58,0xbf4ebd49,0x3f18bf80,0xbf183f80,0xbf4ebd49,
0xbe793f71,0xbf783eac,0x3f78beac,0xbe793f71,0x3f7dbf2c,0x3e163f3e,0xbe16bf3e,0x3f7dbf2c,0xbf04bedb,0x3f5cbf67,0xbf5c3f67,0xbf04bedb,
0x3f313dfb,0xbf393f7e,0x3f80bf1d,0xbcc93f4a,0x3f13bf7f,0x3f51bd97,0xbe2fbf27,0x3f7cbf42,0xbf6a3e89,0x3ecfbf77,0xbf6f3f5f,0xbeb8befc,
0xbe603f65,0xbf7a3ee6,0x3f093ea1,0xbf583f73,0xbf0ebe48,0x3f55bf7b,0xbf0ebe48,0x3f55bf7b,0xbf553f7b,0xbf0ebe48,0xbf553f7b,0xbf0ebe48,
0x3f0e3e48,0xbf553f7b,0x3f0e3e48,0xbf553f7b,0x3f55bf7b,0x3f0e3e48,0x3f55bf7b,0x3f0e3e48,0x3ecf3e89,0xbf6a3f77,0xbeb83f5f,0xbf6f3efc,
0x3f7abf65,0x3e603ee6,0x3f58bea1,0xbf093f73,0xbcc9bf1d,0x3f80bf4a,0x3f31bf7e,0x3f39bdfb,0xbf7c3f27,0x3e2fbf42,0xbf13bd97,0x3f51bf7f,
0xbe79beac,0x3f78bf71,0x3f78bf71,0x3e793eac,0xbf7d3f3e,0x3e16bf2c,0x3e16bf2c,0x3f7dbf3e,0xbf043f67,0xbf5c3edb,0xbf5c3edb,0x3f04bf67,
0x3f18bd49,0xbf4e3f80,0xbf4e3f80,0xbf183d49,0x3d973ecf,0xbf7f3f6a,0xbf423eb8,0x3f27bf6f,0x3f5fbf09,0xbefc3f58,0xbf773f7a,0xbe89be60,
0x3f65bf80,0x3ee63cc9,0xbea13f39,0xbf733f31,0x3dfbbf13,0x3f7ebf51,0x3f1dbe2f,0xbf4a3f7c,0x3dc9bef1,0x3f7fbf62,0xbdc93ef1,0xbf7f3f62,
0xbf223e95,0x3f46bf75,0x3f22be95,0xbf463f75,0xbf7f3f62,0x3dc9bef1,0x3f7fbf62,0xbdc93ef1,0xbf463f75,0xbf223e95,0x3f46bf75,0x3f22be95,
0xbe893f09,0xbf773f58,0x3f5fbf7a,0x3efcbe60,0x3ea1bcc9,0xbf733f80,0x3ee6bf31,0x3f65bf39,0x3f4abf13,0xbf1d3f51,0xbdfbbe2f,0x3f7ebf7c,
0x3f7fbf6f,0xbd973eb8,0xbf273ecf,0x3f42bf6a,0x3edbbf18,0x3f67bf4e,0xbf673f4e,0x3edbbf18,0x3d49be79,0x3f80bf78,0xbf803f78,0x3d49be79,
0xbeac3e16,0x3f71bf7d,0xbf713f7d,0xbeac3e16,0xbf2c3f04,0x3f3ebf5c,0xbf3e3f5c,0xbf2c3f04,0xbf133f27,0xbf513f42,0x3e2fbd97,0xbf7c3f7f,
0xbecf3efc,0xbf6a3f5f,0x3eb8be89,0xbf6f3f77,0xbe603ea1,0xbf7a3f73,0x3f09bee6,0xbf583f65,0xbcc93dfb,0xbf803f7e,0x3f31bf1d,0xbf393f4a,
0x3f803f80,0xbf353f35,0x3f803f80,0xbf353f35,0x3f803f80,0xbf353f35,0x3f803f80,0xbf353f35,0x3f803f80,0xbf353f35,0x3f803f80,0xbf353f35,
0x3f803f80,0xbf353f35,0x3f803f80,0xbf353f35,0x3e2f3d97,0x3f7c3f7f,0x3f513f42,0x3f133f27,0x3eb83e89,0x3f6f3f77,0x3f6a3f5f,0x3ecf3efc,
0x3f093ee6,0x3f583f65,0x3f7a3f73,0x3e603ea1,0x3f313f1d,0x3f393f4a,0x3f803f7e,0x3cc93dfb,0xbf71bf7d,0x3eac3e16,0x3eac3e16,0x3f713f7d,
0xbf3ebf5c,0x3f2c3f04,0x3f2c3f04,0x3f3e3f5c,0xbedbbf18,0x3f673f4e,0x3f673f4e,0x3edb3f18,0xbd49be79,0x3f803f78,0x3f803f78,0x3d493e79,
0xbefcbe60,0xbf5fbf7a,0xbe89bf09,0x3f773f58,0xbf65bf39,0xbee6bf31,0x3ea13cc9,0x3f733f80,0xbf7ebf7c,0x3dfbbe2f,0x3f4a3f13,0x3f1d3f51,
0xbf42bf6a,0x3f273ecf,0x3f7f3f6f,0x3d973eb8,0x3f463f75,0xbf22be95,0xbf46bf75,0x3f223e95,0x3dc93ef1,0xbf7fbf62,0xbdc9bef1,0x3f7f3f62,
0xbf22be95,0xbf46bf75,0x3f223e95,0x3f463f75,0xbf7fbf62,0xbdc9bef1,0x3f7f3f62,0x3dc93ef1,0x3f423eb8,0x3f273f6f,0xbf7fbf6a,0x3d97becf,
0x3f773f7a,0xbe893e60,0xbefcbf58,0x3f5f3f09,0x3ea13f39,0xbf73bf31,0x3ee6bcc9,0x3f653f80,0xbf1dbe2f,0xbf4abf7c,0x3f7e3f51,0x3dfb3f13,
0xbf04bf67,0x3f5c3edb,0xbf5cbedb,0xbf04bf67,0x3f183d49,0x3f4e3f80,0xbf4ebf80,0x3f183d49,0x3f783f71,0xbe793eac,0x3e79beac,0x3f783f71,
0x3e163f2c,0xbf7dbf3e,0x3f7d3f3e,0x3e163f2c,0xbf6fbefc,0xbeb8bf5f,0xbecf3e89,0xbf6abf77,0xbf09bf73,0x3f583ea1,0xbf7abf65,0x3e60bee6,
0x3f393dfb,0x3f313f7e,0x3cc9bf1d,0x3f803f4a,0x3f513f7f,0xbf133d97,0x3f7c3f27,0x3e2f3f42,0x3e483f55,0xbf7bbf0e,0x3e483f55,0xbf7bbf0e,
0xbf7bbf0e,0xbe48bf55,0xbf7bbf0e,0xbe48bf55,0xbe48bf55,0x3f7b3f0e,0xbe48bf55,0x3f7b3f0e,0x3f7b3f0e,0x3e483f55,0x3f7b3f0e,0x3e483f55,
0x3f803f1d,0x3cc93f4a,0x3f393f7e,0xbf313dfb,0xbe2f3f27,0xbf7cbf42,0xbf51bd97,0xbf13bf7f,0xbf6fbf5f,0x3eb8befc,0xbecfbf77,0x3f6a3e89,
0x3f09bea1,0x3f583f73,0x3f7a3ee6,0x3e603f65,0x3e16bf3e,0x3f7d3f2c,0x3f7d3f2c,0xbe163f3e,0x3f5c3f67,0xbf043edb,0xbf043edb,0xbf5cbf67,
0xbf4e3d49,0xbf18bf80,0xbf18bf80,0x3f4ebd49,0xbe79bf71,0x3f783eac,0x3f783eac,0x3e793f71,0xbf73bf39,0x3ea1bf31,0x3f653cc9,0x3ee63f80,
0x3f4abe2f,0x3f1d3f7c,0xbdfb3f51,0xbf7ebf13,0x3d973f6a,0xbf7fbecf,0xbf42bf6f,0x3f27beb8,0xbf5fbf58,0x3efcbf09,0x3f773e60,0x3e893f7a,
0xbef13f22,0xbf62bf46,0x3ef1bf22,0x3f623f46,0xbe95bf7f,0x3f753dc9,0x3e953f7f,0xbf75bdc9,0x3f623f46,0xbef13f22,0xbf62bf46,0x3ef1bf22,
0xbf75bdc9,0xbe95bf7f,0x3f753dc9,0x3e953f7f,0x3f4a3f51,0xbf1d3f13,0xbdfbbf7c,0x3f7e3e2f,0xbf7fbeb8,0x3d97bf6f,0x3f273f6a,0xbf423ecf,
0x3f5fbe60,0x3efc3f7a,0xbf77bf09,0x3e89bf58,0xbee63f39,0xbf65bf31,0x3f73bcc9,0x3ea13f80,0x3f3ebf04,0x3f2c3f5c,0xbf2cbf5c,0x3f3ebf04,
0xbedb3f4e,0xbf67bf18,0x3f673f18,0xbedb3f4e,0x3d49bf78,0x3f803e79,0xbf80be79,0x3d49bf78,0x3eac3f7d,0xbf713e16,0x3f71be16,0x3eac3f7d,
0xbf09bf65,0x3f58bee6,0xbf7abea1,0x3e60bf73,0x3f313f4a,0xbf393f1d,0x3f803dfb,0xbcc93f7e,0xbf51bf27,0x3f13bf42,0xbf7c3d97,0xbe2fbf7f,
0x3f6a3efc,0xbecf3f5f,0x3f6fbe89,0x3eb83f77,0xbf6d3ec4,0xbec4bf6d,0xbf6d3ec4,0xbec4bf6d,0x3f6dbec4,0x3ec43f6d,0x3f6dbec4,0x3ec43f6d,
0xbf6d3ec4,0xbec4bf6d,0xbf6d3ec4,0xbec4bf6d,0x3f6dbec4,0x3ec43f6d,0x3f6dbec4,0x3ec43f6d,0x3e603f73,0xbf7a3ea1,0xbf093f65,0xbf58bee6,
0xbcc9bf7e,0x3f80bdfb,0x3f31bf4a,0x3f393f1d,0xbe2f3f7f,0xbf7cbd97,0xbf513f27,0xbf13bf42,0x3eb8bf77,0x3f6f3e89,0x3f6abefc,0x3ecf3f5f,
0x3f80be79,0x3d493f78,0x3d493f78,0xbf803e79,0xbf71be16,0x3eacbf7d,0x3eacbf7d,0x3f713e16,0x3f3e3f04,0xbf2c3f5c,0xbf2c3f5c,0xbf3ebf04,
0xbedbbf4e,0x3f67bf18,0x3f67bf18,0x3edb3f4e,0x3dfbbf7c,0x3f7ebe2f,0x3f1d3f13,0xbf4a3f51,0xbf273f6a,0xbf42becf,0xbd97bf6f,0x3f7fbeb8,
0x3f77bf09,0x3e893f58,0xbefc3f7a,0xbf5fbe60,0xbf73bcc9,0x3ea1bf80,0x3f65bf31,0x3ee63f39,0xbf753dc9,0x3e95bf7f,0x3f75bdc9,0xbe953f7f,
0x3ef13f22,0xbf623f46,0xbef1bf22,0x3f62bf46,0x3e95bf7f,0x3f75bdc9,0xbe953f7f,0xbf753dc9,0xbf623f46,0xbef1bf22,0x3f62bf46,0x3ef13f22,
0xbee63f80,0xbf653cc9,0x3f73bf39,0x3ea13f31,0x3f7ebf13,0x3dfb3f51,0xbf4abe2f,0x3f1dbf7c,0xbf27beb8,0x3f42bf6f,0xbd973f6a,0xbf7f3ecf,
0xbe893f7a,0xbf773e60,0x3f5fbf58,0x3efc3f09,0x3f4e3d49,0xbf183f80,0x3f18bf80,0x3f4e3d49,0x3e79bf71,0x3f78beac,0xbf783eac,0x3e79bf71,
0xbf7d3f2c,0xbe16bf3e,0x3e163f3e,0xbf7d3f2c,0x3f043edb,0xbf5c3f67,0x3f5cbf67,0x3f043edb,0x3f39bf7e,0x3f313dfb,0x3cc9bf4a,0x3f80bf1d,
0xbf513d97,0x3f13bf7f,0xbf7c3f42,0xbe2fbf27,0xbecf3f77,0xbf6a3e89,0x3eb83efc,0xbf6f3f5f,0x3f7abee6,0xbe603f65,0x3f58bf73,0x3f093ea1,
0xbf0ebe48,0x3f55bf7b,0xbf0ebe48,0x3f55bf7b,0xbf553f7b,0xbf0ebe48,0xbf553f7b,0xbf0ebe48,0x3f0e3e48,0xbf553f7b,0x3f0e3e48,0xbf553f7b,
0x3f55bf7b,0x3f0e3e48,0x3f55bf7b,0x3f0e3e48,0xbf6a3f77,0xbecfbe89,0xbf6f3efc,0x3eb8bf5f,0x3e603ee6,0xbf7a3f65,0xbf093f73,0xbf583ea1,
0x3f80bf4a,0x3cc93f1d,0x3f39bdfb,0xbf313f7e,0x3e2fbf42,0x3f7cbf27,0x3f51bf7f,0x3f133d97,0x3e793eac,0xbf783f71,0xbf783f71,0xbe79beac,
0x3f7dbf3e,0xbe163f2c,0xbe163f2c,0xbf7d3f3e,0x3f04bf67,0x3f5cbedb,0x3f5cbedb,0xbf043f67,0xbf183d49,0x3f4ebf80,0x3f4ebf80,0x3f18bd49,
0x3f7fbf6a,0x3d973ecf,0xbf273f6f,0xbf423eb8,0x3efcbf58,0x3f5fbf09,0x3e893e60,0xbf773f7a,0xbee6bcc9,0x3f65bf80,0x3f73bf31,0xbea13f39,
0xbf7e3f51,0x3dfbbf13,0x3f4abf7c,0x3f1dbe2f,0x3dc9bef1,0x3f7fbf62,0xbdc93ef1,0xbf7f3f62,0xbf223e95,0x3f46bf75,0x3f22be95,0xbf463f75,
0xbf7f3f62,0x3dc9bef1,0x3f7fbf62,0xbdc93ef1,0xbf463f75,0xbf223e95,0x3f46bf75,0x3f22be95,0xbf773f58,0x3e89bf09,0x3efcbe60,0xbf5f3f7a,
0xbf733f80,0xbea13cc9,0x3f65bf39,0xbee63f31,0xbf1d3f51,0xbf4a3f13,0x3f7ebf7c,0x3dfb3e2f,0xbd973eb8,0xbf7f3f6f,0x3f42bf6a,0x3f27becf,
0xbedb3f18,0xbf673f4e,0x3f67bf4e,0xbedb3f18,0xbd493e79,0xbf803f78,0x3f80bf78,0xbd493e79,0x3eacbe16,0xbf713f7d,0x3f71bf7d,0x3eacbe16,
0x3f2cbf04,0xbf3e3f5c,0x3f3ebf5c,0x3f2cbf04,0x3f51bf42,0xbf133f27,0x3f7cbf7f,0x3e2fbd97,0x3f6abf5f,0xbecf3efc,0x3f6fbf77,0x3eb8be89,
0x3f7abf73,0xbe603ea1,0x3f58bf65,0x3f09bee6,0x3f80bf7e,0xbcc93dfb,0x3f39bf4a,0x3f31bf1d,0x3f803f80,0x3f803f80,0x3f803f80,0x3f803f80,
0x3f803f80,0x3f803f80,0x3f803f80,0x3f803f80,0x3f803f80,0x3f803f80,0x3f803f80,0x3f803f80,0x3f803f80,0x3f803f80,0x3f803f80,0x3f803f80,
0x0,0x0,0x0,0x0,0x0,0x0,0x0,0x0,0x0,0x0,0x0,0x0,
0x0,0x0,0x0,0x0,0xbe480000,0xbf0ebec4,0xbf55bf35,0xbf7bbf6d,0x3f7b3f80,0x3f553f6d,0x3f0e3f35,0x3e483ec4,
0x3e480000,0x3f0e3ec4,0x3f553f35,0x3f7b3f6d,0xbf7bbf80,0xbf55bf6d,0xbf0ebf35,0xbe48bec4,0x3f7b3f80,0x3f553f6d,0x3f0e3f35,0x3e483ec4,
0x3e480000,0x3f0e3ec4,0x3f553f35,0x3f7b3f6d,0xbf7bbf80,0xbf55bf6d,0xbf0ebf35,0xbe48bec4,0xbe480000,0xbf0ebec4,0xbf55bf35,0xbf7bbf6d,
0x3f6d3f80,0x3ec43f35,0xbec40000,0xbf6dbf35,0xbf6dbf80,0xbec4bf35,0x3ec40000,0x3f6d3f35,0x3f6d3f80,0x3ec43f35,0xbec40000,0xbf6dbf35,
0xbf6dbf80,0xbec4bf35,0x3ec40000,0x3f6d3f35,0x3ec40000,0x3f6d3f35,0x3f6d3f80,0x3ec43f35,0xbec40000,0xbf6dbf35,0xbf6dbf80,0xbec4bf35,
0x3ec40000,0x3f6d3f35,0x3f6d3f80,0x3ec43f35,0xbec40000,0xbf6dbf35,0xbf6dbf80,0xbec4bf35,0xbf0e0000,0xbf7bbf6d,0xbe48bf35,0x3f553ec4,
0xbf55bf80,0x3e48bec4,0x3f7b3f35,0x3f0e3f6d,0x3f0e0000,0x3f7b3f6d,0x3e483f35,0xbf55bec4,0x3f553f80,0xbe483ec4,0xbf7bbf35,0xbf0ebf6d,
0x3f553f80,0xbe483ec4,0xbf7bbf35,0xbf0ebf6d,0xbf0e0000,0xbf7bbf6d,0xbe48bf35,0x3f553ec4,0xbf55bf80,0x3e48bec4,0x3f7b3f35,0x3f0e3f6d,
0x3f0e0000,0x3f7b3f6d,0x3e483f35,0xbf55bec4,0x3f350000,0x3f353f80,0xbf350000,0xbf35bf80,0x3f350000,0x3f353f80,0xbf350000,0xbf35bf80,
0x3f350000,0x3f353f80,0xbf350000,0xbf35bf80,0x3f350000,0x3f353f80,0xbf350000,0xbf35bf80,0x3f353f80,0xbf350000,0xbf35bf80,0x3f350000,
0x3f353f80,0xbf350000,0xbf35bf80,0x3f350000,0x3f353f80,0xbf350000,0xbf35bf80,0x3f350000,0x3f353f80,0xbf350000,0xbf35bf80,0x3f350000,
0x3f0e3f80,0xbf7bbec4,0x3e48bf35,0x3f553f6d,0x3f550000,0x3e483f6d,0xbf7bbf35,0x3f0ebec4,0xbf0ebf80,0x3f7b3ec4,0xbe483f35,0xbf55bf6d,
0xbf550000,0xbe48bf6d,0x3f7b3f35,0xbf0e3ec4,0xbf550000,0xbe48bf6d,0x3f7b3f35,0xbf0e3ec4,0x3f0e3f80,0xbf7bbec4,0x3e48bf35,0x3f553f6d,
0x3f550000,0x3e483f6d,0xbf7bbf35,0x3f0ebec4,0xbf0ebf80,0x3f7b3ec4,0xbe483f35,0xbf55bf6d,0x3f6d0000,0xbec43f35,0xbec4bf80,0x3f6d3f35,
0xbf6d0000,0x3ec4bf35,0x3ec43f80,0xbf6dbf35,0x3f6d0000,0xbec43f35,0xbec4bf80,0x3f6d3f35,0xbf6d0000,0x3ec4bf35,0x3ec43f80,0xbf6dbf35,
0x3ec43f80,0xbf6dbf35,0x3f6d0000,0xbec43f35,0xbec4bf80,0x3f6d3f35,0xbf6d0000,0x3ec4bf35,0x3ec43f80,0xbf6dbf35,0x3f6d0000,0xbec43f35,
0xbec4bf80,0x3f6d3f35,0xbf6d0000,0x3ec4bf35,0x3e483f80,0xbf0ebf6d,0x3f553f35,0xbf7bbec4,0xbf7b0000,0x3f55bec4,0xbf0e3f35,0x3e48bf6d,
0xbe48bf80,0x3f0e3f6d,0xbf55bf35,0x3f7b3ec4,0x3f7b0000,0xbf553ec4,0x3f0ebf35,0xbe483f6d,0xbf7b0000,0x3f55bec4,0xbf0e3f35,0x3e48bf6d,
0xbe48bf80,0x3f0e3f6d,0xbf55bf35,0x3f7b3ec4,0x3f7b0000,0xbf553ec4,0x3f0ebf35,0xbe483f6d,0x3e483f80,0xbf0ebf6d,0x3f553f35,0xbf7bbec4,
0x3f80,0xbf80,0x3f80,0xbf80,0x3f80,0xbf80,0x3f80,0xbf80,0x3f80,0xbf80,0x3f80,0xbf80,
0x3f80,0xbf80,0x3f80,0xbf80,0x3f800000,0xbf800000,0x3f800000,0xbf800000,0x3f800000,0xbf800000,0x3f800000,0xbf800000,
0x3f800000,0xbf800000,0x3f800000,0xbf800000,0x3f800000,0xbf800000,0x3f800000,0xbf800000,0xbf7b0000,0x3f553ec4,0xbf0ebf35,0x3e483f6d,
0xbe483f80,0x3f0ebf6d,0xbf553f35,0x3f7bbec4,0x3f7b0000,0xbf55bec4,0x3f0e3f35,0xbe48bf6d,0x3e48bf80,0xbf0e3f6d,0x3f55bf35,0xbf7b3ec4,
0xbe483f80,0x3f0ebf6d,0xbf553f35,0x3f7bbec4,0x3f7b0000,0xbf55bec4,0x3f0e3f35,0xbe48bf6d,0x3e48bf80,0xbf0e3f6d,0x3f55bf35,0xbf7b3ec4,
0xbf7b0000,0x3f553ec4,0xbf0ebf35,0x3e483f6d,0xbec43f80,0x3f6dbf35,0xbf6d0000,0x3ec43f35,0x3ec4bf80,0xbf6d3f35,0x3f6d0000,0xbec4bf35,
0xbec43f80,0x3f6dbf35,0xbf6d0000,0x3ec43f35,0x3ec4bf80,0xbf6d3f35,0x3f6d0000,0xbec4bf35,0x3f6d0000,0xbec4bf35,0xbec43f80,0x3f6dbf35,
0xbf6d0000,0x3ec43f35,0x3ec4bf80,0xbf6d3f35,0x3f6d0000,0xbec4bf35,0xbec43f80,0x3f6dbf35,0xbf6d0000,0x3ec43f35,0x3ec4bf80,0xbf6d3f35,
0xbf550000,0xbe483f6d,0x3f7bbf35,0xbf0ebec4,0x3f0ebf80,0xbf7b3ec4,0x3e483f35,0x3f55bf6d,0x3f550000,0x3e48bf6d,0xbf7b3f35,0x3f0e3ec4,
0xbf0e3f80,0x3f7bbec4,0xbe48bf35,0xbf553f6d,0xbf0e3f80,0x3f7bbec4,0xbe48bf35,0xbf553f6d,0xbf550000,0xbe483f6d,0x3f7bbf35,0xbf0ebec4,
0x3f0ebf80,0xbf7b3ec4,0x3e483f35,0x3f55bf6d,0x3f550000,0x3e48bf6d,0xbf7b3f35,0x3f0e3ec4,0x3f350000,0x3f35bf80,0xbf350000,0xbf353f80,
0x3f350000,0x3f35bf80,0xbf350000,0xbf353f80,0x3f350000,0x3f35bf80,0xbf350000,0xbf353f80,0x3f350000,0x3f35bf80,0xbf350000,0xbf353f80,
0xbf353f80,0x3f350000,0x3f35bf80,0xbf350000,0xbf353f80,0x3f350000,0x3f35bf80,0xbf350000,0xbf353f80,0x3f350000,0x3f35bf80,0xbf350000,
0xbf353f80,0x3f350000,0x3f35bf80,0xbf350000,0xbf553f80,0x3e483ec4,0x3f7bbf35,0x3f0ebf6d,0x3f0e0000,0x3f7bbf6d,0x3e48bf35,0xbf553ec4,
0x3f55bf80,0xbe48bec4,0xbf7b3f35,0xbf0e3f6d,0xbf0e0000,0xbf7b3f6d,0xbe483f35,0x3f55bec4,0xbf0e0000,0xbf7b3f6d,0xbe483f35,0x3f55bec4,
0xbf553f80,0x3e483ec4,0x3f7bbf35,0x3f0ebf6d,0x3f0e0000,0x3f7bbf6d,0x3e48bf35,0xbf553ec4,0x3f55bf80,0xbe48bec4,0xbf7b3f35,0xbf0e3f6d,
0x3ec40000,0x3f6dbf35,0x3f6dbf80,0x3ec4bf35,0xbec40000,0xbf6d3f35,0xbf6d3f80,0xbec43f35,0x3ec40000,0x3f6dbf35,0x3f6dbf80,0x3ec4bf35,
0xbec40000,0xbf6d3f35,0xbf6d3f80,0xbec43f35,0xbf6d3f80,0xbec43f35,0x3ec40000,0x3f6dbf35,0x3f6dbf80,0x3ec4bf35,0xbec40000,0xbf6d3f35,
0xbf6d3f80,0xbec43f35,0x3ec40000,0x3f6dbf35,0x3f6dbf80,0x3ec4bf35,0xbec40000,0xbf6d3f35,0xbf7b3f80,0xbf553f6d,0xbf0e3f35,0xbe483ec4,
0xbe480000,0xbf0e3ec4,0xbf553f35,0xbf7b3f6d,0x3f7bbf80,0x3f55bf6d,0x3f0ebf35,0x3e48bec4,0x3e480000,0x3f0ebec4,0x3f55bf35,0x3f7bbf6d,
0xbe480000,0xbf0e3ec4,0xbf553f35,0xbf7b3f6d,0x3f7bbf80,0x3f55bf6d,0x3f0ebf35,0x3e48bec4,0x3e480000,0x3f0ebec4,0x3f55bf35,0x3f7bbf6d,
0xbf7b3f80,0xbf553f6d,0xbf0e3f35,0xbe483ec4,0xbf803f80,0xbf803f80,0xbf803f80,0xbf803f80,0xbf803f80,0xbf803f80,0xbf803f80,0xbf803f80,
0xbf803f80,0xbf803f80,0xbf803f80,0xbf803f80,0xbf803f80,0xbf803f80,0xbf803f80,0xbf803f80,0x0,0x0,0x0,0x0,
0x0,0x0,0x0,0x0,0x0,0x0,0x0,0x0,0x0,0x0,0x0,0x0,
0x3e480000,0x3f0ebec4,0x3f55bf35,0x3f7bbf6d,0xbf7b3f80,0xbf553f6d,0xbf0e3f35,0xbe483ec4,0xbe480000,0xbf0e3ec4,0xbf553f35,0xbf7b3f6d,
0x3f7bbf80,0x3f55bf6d,0x3f0ebf35,0x3e48bec4,0xbf7b3f80,0xbf553f6d,0xbf0e3f35,0xbe483ec4,0xbe480000,0xbf0e3ec4,0xbf553f35,0xbf7b3f6d,
0x3f7bbf80,0x3f55bf6d,0x3f0ebf35,0x3e48bec4,0x3e480000,0x3f0ebec4,0x3f55bf35,0x3f7bbf6d,0xbf6d3f80,0xbec43f35,0x3ec40000,0x3f6dbf35,
0x3f6dbf80,0x3ec4bf35,0xbec40000,0xbf6d3f35,0xbf6d3f80,0xbec43f35,0x3ec40000,0x3f6dbf35,0x3f6dbf80,0x3ec4bf35,0xbec40000,0xbf6d3f35,
0xbec40000,0xbf6d3f35,0xbf6d3f80,0xbec43f35,0x3ec40000,0x3f6dbf35,0x3f6dbf80,0x3ec4bf35,0xbec40000,0xbf6d3f35,0xbf6d3f80,0xbec43f35,
0x3ec40000,0x3f6dbf35,0x3f6dbf80,0x3ec4bf35,0x3f0e0000,0x3f7bbf6d,0x3e48bf35,0xbf553ec4,0x3f55bf80,0xbe48bec4,0xbf7b3f35,0xbf0e3f6d,
0xbf0e0000,0xbf7b3f6d,0xbe483f35,0x3f55bec4,0xbf553f80,0x3e483ec4,0x3f7bbf35,0x3f0ebf6d,0xbf553f80,0x3e483ec4,0x3f7bbf35,0x3f0ebf6d,
0x3f0e0000,0x3f7bbf6d,0x3e48bf35,0xbf553ec4,0x3f55bf80,0xbe48bec4,0xbf7b3f35,0xbf0e3f6d,0xbf0e0000,0xbf7b3f6d,0xbe483f35,0x3f55bec4,
0xbf350000,0xbf353f80,0x3f350000,0x3f35bf80,0xbf350000,0xbf353f80,0x3f350000,0x3f35bf80,0xbf350000,0xbf353f80,0x3f350000,0x3f35bf80,
0xbf350000,0xbf353f80,0x3f350000,0x3f35bf80,0xbf353f80,0x3f350000,0x3f35bf80,0xbf350000,0xbf353f80,0x3f350000,0x3f35bf80,0xbf350000,
0xbf353f80,0x3f350000,0x3f35bf80,0xbf350000,0xbf353f80,0x3f350000,0x3f35bf80,0xbf350000,0xbf0e3f80,0x3f7bbec4,0xbe48bf35,0xbf553f6d,
0xbf550000,0xbe483f6d,0x3f7bbf35,0xbf0ebec4,0x3f0ebf80,0xbf7b3ec4,0x3e483f35,0x3f55bf6d,0x3f550000,0x3e48bf6d,0xbf7b3f35,0x3f0e3ec4,
0x3f550000,0x3e48bf6d,0xbf7b3f35,0x3f0e3ec4,0xbf0e3f80,0x3f7bbec4,0xbe48bf35,0xbf553f6d,0xbf550000,0xbe483f6d,0x3f7bbf35,0xbf0ebec4,
0x3f0ebf80,0xbf7b3ec4,0x3e483f35,0x3f55bf6d,0xbf6d0000,0x3ec43f35,0x3ec4bf80,0xbf6d3f35,0x3f6d0000,0xbec4bf35,0xbec43f80,0x3f6dbf35,
0xbf6d0000,0x3ec43f35,0x3ec4bf80,0xbf6d3f35,0x3f6d0000,0xbec4bf35,0xbec43f80,0x3f6dbf35,0xbec43f80,0x3f6dbf35,0xbf6d0000,0x3ec43f35,
0x3ec4bf80,0xbf6d3f35,0x3f6d0000,0xbec4bf35,0xbec43f80,0x3f6dbf35,0xbf6d0000,0x3ec43f35,0x3ec4bf80,0xbf6d3f35,0x3f6d0000,0xbec4bf35,
0xbe483f80,0x3f0ebf6d,0xbf553f35,0x3f7bbec4,0x3f7b0000,0xbf55bec4,0x3f0e3f35,0xbe48bf6d,0x3e48bf80,0xbf0e3f6d,0x3f55bf35,0xbf7b3ec4,
0xbf7b0000,0x3f553ec4,0xbf0ebf35,0x3e483f6d,0x3f7b0000,0xbf55bec4,0x3f0e3f35,0xbe48bf6d,0x3e48bf80,0xbf0e3f6d,0x3f55bf35,0xbf7b3ec4,
0xbf7b0000,0x3f553ec4,0xbf0ebf35,0x3e483f6d,0xbe483f80,0x3f0ebf6d,0xbf553f35,0x3f7bbec4,0x3f80,0xbf80,0x3f80,0xbf80,
0x3f80,0xbf80,0x3f80,0xbf80,0x3f80,0xbf80,0x3f80,0xbf80,0x3f80,0xbf80,0x3f80,0xbf80,
0xbf800000,0x3f800000,0xbf800000,0x3f800000,0xbf800000,0x3f800000,0xbf800000,0x3f800000,0xbf800000,0x3f800000,0xbf800000,0x3f800000,
0xbf800000,0x3f800000,0xbf800000,0x3f800000,0x3f7b0000,0xbf553ec4,0x3f0ebf35,0xbe483f6d,0x3e483f80,0xbf0ebf6d,0x3f553f35,0xbf7bbec4,
0xbf7b0000,0x3f55bec4,0xbf0e3f35,0x3e48bf6d,0xbe48bf80,0x3f0e3f6d,0xbf55bf35,0x3f7b3ec4,0x3e483f80,0xbf0ebf6d,0x3f553f35,0xbf7bbec4,
0xbf7b0000,0x3f55bec4,0xbf0e3f35,0x3e48bf6d,0xbe48bf80,0x3f0e3f6d,0xbf55bf35,0x3f7b3ec4,0x3f7b0000,0xbf553ec4,0x3f0ebf35,0xbe483f6d,
0x3ec43f80,0xbf6dbf35,0x3f6d0000,0xbec43f35,0xbec4bf80,0x3f6d3f35,0xbf6d0000,0x3ec4bf35,0x3ec43f80,0xbf6dbf35,0x3f6d0000,0xbec43f35,
0xbec4bf80,0x3f6d3f35,0xbf6d0000,0x3ec4bf35,0xbf6d0000,0x3ec4bf35,0x3ec43f80,0xbf6dbf35,0x3f6d0000,0xbec43f35,0xbec4bf80,0x3f6d3f35,
0xbf6d0000,0x3ec4bf35,0x3ec43f80,0xbf6dbf35,0x3f6d0000,0xbec43f35,0xbec4bf80,0x3f6d3f35,0x3f550000,0x3e483f6d,0xbf7bbf35,0x3f0ebec4,
0xbf0ebf80,0x3f7b3ec4,0xbe483f35,0xbf55bf6d,0xbf550000,0xbe48bf6d,0x3f7b3f35,0xbf0e3ec4,0x3f0e3f80,0xbf7bbec4,0x3e48bf35,0x3f553f6d,
0x3f0e3f80,0xbf7bbec4,0x3e48bf35,0x3f553f6d,0x3f550000,0x3e483f6d,0xbf7bbf35,0x3f0ebec4,0xbf0ebf80,0x3f7b3ec4,0xbe483f35,0xbf55bf6d,
0xbf550000,0xbe48bf6d,0x3f7b3f35,0xbf0e3ec4,0xbf350000,0xbf35bf80,0x3f350000,0x3f353f80,0xbf350000,0xbf35bf80,0x3f350000,0x3f353f80,
0xbf350000,0xbf35bf80,0x3f350000,0x3f353f80,0xbf350000,0xbf35bf80,0x3f350000,0x3f353f80,0x3f353f80,0xbf350000,0xbf35bf80,0x3f350000,
0x3f353f80,0xbf350000,0xbf35bf80,0x3f350000,0x3f353f80,0xbf350000,0xbf35bf80,0x3f350000,0x3f353f80,0xbf350000,0xbf35bf80,0x3f350000,
0x3f553f80,0xbe483ec4,0xbf7bbf35,0xbf0ebf6d,0xbf0e0000,0xbf7bbf6d,0xbe48bf35,0x3f553ec4,0xbf55bf80,0x3e48bec4,0x3f7b3f35,0x3f0e3f6d,
0x3f0e0000,0x3f7b3f6d,0x3e483f35,0xbf55bec4,0x3f0e0000,0x3f7b3f6d,0x3e483f35,0xbf55bec4,0x3f553f80,0xbe483ec4,0xbf7bbf35,0xbf0ebf6d,
0xbf0e0000,0xbf7bbf6d,0xbe48bf35,0x3f553ec4,0xbf55bf80,0x3e48bec4,0x3f7b3f35,0x3f0e3f6d,0xbec40000,0xbf6dbf35,0xbf6dbf80,0xbec4bf35,
0x3ec40000,0x3f6d3f35,0x3f6d3f80,0x3ec43f35,0xbec40000,0xbf6dbf35,0xbf6dbf80,0xbec4bf35,0x3ec40000,0x3f6d3f35,0x3f6d3f80,0x3ec43f35,
0x3f6d3f80,0x3ec43f35,0xbec40000,0xbf6dbf35,0xbf6dbf80,0xbec4bf35,0x3ec40000,0x3f6d3f35,0x3f6d3f80,0x3ec43f35,0xbec40000,0xbf6dbf35,
0xbf6dbf80,0xbec4bf35,0x3ec40000,0x3f6d3f35,0x3f7b3f80,0x3f553f6d,0x3f0e3f35,0x3e483ec4,0x3e480000,0x3f0e3ec4,0x3f553f35,0x3f7b3f6d,
0xbf7bbf80,0xbf55bf6d,0xbf0ebf35,0xbe48bec4,0xbe480000,0xbf0ebec4,0xbf55bf35,0xbf7bbf6d,0x3e480000,0x3f0e3ec4,0x3f553f35,0x3f7b3f6d,
0xbf7bbf80,0xbf55bf6d,0xbf0ebf35,0xbe48bec4,0xbe480000,0xbf0ebec4,0xbf55bf35,0xbf7bbf6d,0x3f7b3f80,0x3f553f6d,0x3f0e3f35,0x3e483ec4,
0x80008000,0x80008000,0x80008000,0x80008000,0x80008000,0x80008000,0x80008000,0x80008000,0x80008000,0x80008000,0x80008000,0x80008000,
0x80008000,0x80008000,0x80008000,0x80008000,0x3f803f80,0x3f803f80,0x3f803f80,0x3f803f80,0x3f803f80,0x3f803f80,0x3f803f80,0x3f803f80,
0x3f803f80,0x3f803f80,0x3f803f80,0x3f803f80,0x3f803f80,0x3f803f80,0x3f803f80,0x3f803f80,0xbf7bbf80,0xbf55bf6d,0xbf0ebf35,0xbe48bec4,
0xbe488000,0xbf0ebec4,0xbf55bf35,0xbf7bbf6d,0x3f7b3f80,0x3f553f6d,0x3f0e3f35,0x3e483ec4,0x3e488000,0x3f0e3ec4,0x3f553f35,0x3f7b3f6d,
0xbe480000,0xbf0ebec4,0xbf55bf35,0xbf7bbf6d,0x3f7b3f80,0x3f553f6d,0x3f0e3f35,0x3e483ec4,0x3e480000,0x3f0e3ec4,0x3f553f35,0x3f7b3f6d,
0xbf7bbf80,0xbf55bf6d,0xbf0ebf35,0xbe48bec4,0xbec48000,0xbf6dbf35,0xbf6dbf80,0xbec4bf35,0x3ec48000,0x3f6d3f35,0x3f6d3f80,0x3ec43f35,
0xbec48000,0xbf6dbf35,0xbf6dbf80,0xbec4bf35,0x3ec48000,0x3f6d3f35,0x3f6d3f80,0x3ec43f35,0x3f6d3f80,0x3ec43f35,0xbec40000,0xbf6dbf35,
0xbf6dbf80,0xbec4bf35,0x3ec40000,0x3f6d3f35,0x3f6d3f80,0x3ec43f35,0xbec40000,0xbf6dbf35,0xbf6dbf80,0xbec4bf35,0x3ec40000,0x3f6d3f35,
0xbf55bf80,0x3e48bec4,0x3f7b3f35,0x3f0e3f6d,0x3f0e8000,0x3f7b3f6d,0x3e483f35,0xbf55bec4,0x3f553f80,0xbe483ec4,0xbf7bbf35,0xbf0ebf6d,
0xbf0e8000,0xbf7bbf6d,0xbe48bf35,0x3f553ec4,0xbf0e0000,0xbf7bbf6d,0xbe48bf35,0x3f553ec4,0xbf55bf80,0x3e48bec4,0x3f7b3f35,0x3f0e3f6d,
0x3f0e0000,0x3f7b3f6d,0x3e483f35,0xbf55bec4,0x3f553f80,0xbe483ec4,0xbf7bbf35,0xbf0ebf6d,0x3f353f80,0xbf350000,0xbf35bf80,0x3f350000,
0x3f353f80,0xbf350000,0xbf35bf80,0x3f350000,0x3f353f80,0xbf350000,0xbf35bf80,0x3f350000,0x3f353f80,0xbf350000,0xbf35bf80,0x3f350000,
0xbf358000,0xbf35bf80,0x3f358000,0x3f353f80,0xbf358000,0xbf35bf80,0x3f358000,0x3f353f80,0xbf358000,0xbf35bf80,0x3f358000,0x3f353f80,
0xbf358000,0xbf35bf80,0x3f358000,0x3f353f80,0xbf550000,0xbe48bf6d,0x3f7b3f35,0xbf0e3ec4,0x3f0e3f80,0xbf7bbec4,0x3e48bf35,0x3f553f6d,
0x3f550000,0x3e483f6d,0xbf7bbf35,0x3f0ebec4,0xbf0ebf80,0x3f7b3ec4,0xbe483f35,0xbf55bf6d,0xbf0ebf80,0x3f7b3ec4,0xbe483f35,0xbf55bf6d,
0xbf558000,0xbe48bf6d,0x3f7b3f35,0xbf0e3ec4,0x3f0e3f80,0xbf7bbec4,0x3e48bf35,0x3f553f6d,0x3f558000,0x3e483f6d,0xbf7bbf35,0x3f0ebec4,
0x3ec43f80,0xbf6dbf35,0x3f6d0000,0xbec43f35,0xbec4bf80,0x3f6d3f35,0xbf6d0000,0x3ec4bf35,0x3ec43f80,0xbf6dbf35,0x3f6d0000,0xbec43f35,
0xbec4bf80,0x3f6d3f35,0xbf6d0000,0x3ec4bf35,0xbf6d8000,0x3ec4bf35,0x3ec43f80,0xbf6dbf35,0x3f6d8000,0xbec43f35,0xbec4bf80,0x3f6d3f35,
0xbf6d8000,0x3ec4bf35,0x3ec43f80,0xbf6dbf35,0x3f6d8000,0xbec43f35,0xbec4bf80,0x3f6d3f35,0xbf7b0000,0x3f55bec4,0xbf0e3f35,0x3e48bf6d,
0xbe48bf80,0x3f0e3f6d,0xbf55bf35,0x3f7b3ec4,0x3f7b0000,0xbf553ec4,0x3f0ebf35,0xbe483f6d,0x3e483f80,0xbf0ebf6d,0x3f553f35,0xbf7bbec4,
0xbe48bf80,0x3f0e3f6d,0xbf55bf35,0x3f7b3ec4,0x3f7b8000,0xbf553ec4,0x3f0ebf35,0xbe483f6d,0x3e483f80,0xbf0ebf6d,0x3f553f35,0xbf7bbec4,
0xbf7b8000,0x3f55bec4,0xbf0e3f35,0x3e48bf6d,0xbf808000,0x3f808000,0xbf808000,0x3f808000,0xbf808000,0x3f808000,0xbf808000,0x3f808000,
0xbf808000,0x3f808000,0xbf808000,0x3f808000,0xbf808000,0x3f808000,0xbf808000,0x3f808000,0x3f80,0xbf80,0x3f80,0xbf80,
0x3f80,0xbf80,0x3f80,0xbf80,0x3f80,0xbf80,0x3f80,0xbf80,0x3f80,0xbf80,0x3f80,0xbf80,
0x3e48bf80,0xbf0e3f6d,0x3f55bf35,0xbf7b3ec4,0xbf7b8000,0x3f553ec4,0xbf0ebf35,0x3e483f6d,0xbe483f80,0x3f0ebf6d,0xbf553f35,0x3f7bbec4,
0x3f7b8000,0xbf55bec4,0x3f0e3f35,0xbe48bf6d,0xbf7b0000,0x3f553ec4,0xbf0ebf35,0x3e483f6d,0xbe483f80,0x3f0ebf6d,0xbf553f35,0x3f7bbec4,
0x3f7b0000,0xbf55bec4,0x3f0e3f35,0xbe48bf6d,0x3e48bf80,0xbf0e3f6d,0x3f55bf35,0xbf7b3ec4,0xbf6d8000,0x3ec43f35,0x3ec4bf80,0xbf6d3f35,
0x3f6d8000,0xbec4bf35,0xbec43f80,0x3f6dbf35,0xbf6d8000,0x3ec43f35,0x3ec4bf80,0xbf6d3f35,0x3f6d8000,0xbec4bf35,0xbec43f80,0x3f6dbf35,
0xbec43f80,0x3f6dbf35,0xbf6d0000,0x3ec43f35,0x3ec4bf80,0xbf6d3f35,0x3f6d0000,0xbec4bf35,0xbec43f80,0x3f6dbf35,0xbf6d0000,0x3ec43f35,
0x3ec4bf80,0xbf6d3f35,0x3f6d0000,0xbec4bf35,0x3f0ebf80,0xbf7b3ec4,0x3e483f35,0x3f55bf6d,0x3f558000,0x3e48bf6d,0xbf7b3f35,0x3f0e3ec4,
0xbf0e3f80,0x3f7bbec4,0xbe48bf35,0xbf553f6d,0xbf558000,0xbe483f6d,0x3f7bbf35,0xbf0ebec4,0xbf550000,0xbe483f6d,0x3f7bbf35,0xbf0ebec4,
0x3f0ebf80,0xbf7b3ec4,0x3e483f35,0x3f55bf6d,0x3f550000,0x3e48bf6d,0xbf7b3f35,0x3f0e3ec4,0xbf0e3f80,0x3f7bbec4,0xbe48bf35,0xbf553f6d,
0xbf353f80,0x3f350000,0x3f35bf80,0xbf350000,0xbf353f80,0x3f350000,0x3f35bf80,0xbf350000,0xbf353f80,0x3f350000,0x3f35bf80,0xbf350000,
0xbf353f80,0x3f350000,0x3f35bf80,0xbf350000,0xbf358000,0xbf353f80,0x3f358000,0x3f35bf80,0xbf358000,0xbf353f80,0x3f358000,0x3f35bf80,
0xbf358000,0xbf353f80,0x3f358000,0x3f35bf80,0xbf358000,0xbf353f80,0x3f358000,0x3f35bf80,0xbf0e0000,0xbf7b3f6d,0xbe483f35,0x3f55bec4,
0xbf553f80,0x3e483ec4,0x3f7bbf35,0x3f0ebf6d,0x3f0e0000,0x3f7bbf6d,0x3e48bf35,0xbf553ec4,0x3f55bf80,0xbe48bec4,0xbf7b3f35,0xbf0e3f6d,
0x3f55bf80,0xbe48bec4,0xbf7b3f35,0xbf0e3f6d,0xbf0e8000,0xbf7b3f6d,0xbe483f35,0x3f55bec4,0xbf553f80,0x3e483ec4,0x3f7bbf35,0x3f0ebf6d,
0x3f0e8000,0x3f7bbf6d,0x3e48bf35,0xbf553ec4,0xbf6d3f80,0xbec43f35,0x3ec40000,0x3f6dbf35,0x3f6dbf80,0x3ec4bf35,0xbec40000,0xbf6d3f35,
0xbf6d3f80,0xbec43f35,0x3ec40000,0x3f6dbf35,0x3f6dbf80,0x3ec4bf35,0xbec40000,0xbf6d3f35,0xbec48000,0xbf6d3f35,0xbf6d3f80,0xbec43f35,
0x3ec48000,0x3f6dbf35,0x3f6dbf80,0x3ec4bf35,0xbec48000,0xbf6d3f35,0xbf6d3f80,0xbec43f35,0x3ec48000,0x3f6dbf35,0x3f6dbf80,0x3ec4bf35,
0xbe480000,0xbf0e3ec4,0xbf553f35,0xbf7b3f6d,0x3f7bbf80,0x3f55bf6d,0x3f0ebf35,0x3e48bec4,0x3e480000,0x3f0ebec4,0x3f55bf35,0x3f7bbf6d,
0xbf7b3f80,0xbf553f6d,0xbf0e3f35,0xbe483ec4,0x3f7bbf80,0x3f55bf6d,0x3f0ebf35,0x3e48bec4,0x3e488000,0x3f0ebec4,0x3f55bf35,0x3f7bbf6d,
0xbf7b3f80,0xbf553f6d,0xbf0e3f35,0xbe483ec4,0xbe488000,0xbf0e3ec4,0xbf553f35,0xbf7b3f6d,0x80008000,0x80008000,0x80008000,0x80008000,
0x80008000,0x80008000,0x80008000,0x80008000,0x80008000,0x80008000,0x80008000,0x80008000,0x80008000,0x80008000,0x80008000,0x80008000,
0xbf803f80,0xbf803f80,0xbf803f80,0xbf803f80,0xbf803f80,0xbf803f80,0xbf803f80,0xbf803f80,0xbf803f80,0xbf803f80,0xbf803f80,0xbf803f80,
0xbf803f80,0xbf803f80,0xbf803f80,0xbf803f80,0x3f7bbf80,0x3f55bf6d,0x3f0ebf35,0x3e48bec4,0x3e488000,0x3f0ebec4,0x3f55bf35,0x3f7bbf6d,
0xbf7b3f80,0xbf553f6d,0xbf0e3f35,0xbe483ec4,0xbe488000,0xbf0e3ec4,0xbf553f35,0xbf7b3f6d,0x3e480000,0x3f0ebec4,0x3f55bf35,0x3f7bbf6d,
0xbf7b3f80,0xbf553f6d,0xbf0e3f35,0xbe483ec4,0xbe480000,0xbf0e3ec4,0xbf553f35,0xbf7b3f6d,0x3f7bbf80,0x3f55bf6d,0x3f0ebf35,0x3e48bec4,
0x3ec48000,0x3f6dbf35,0x3f6dbf80,0x3ec4bf35,0xbec48000,0xbf6d3f35,0xbf6d3f80,0xbec43f35,0x3ec48000,0x3f6dbf35,0x3f6dbf80,0x3ec4bf35,
0xbec48000,0xbf6d3f35,0xbf6d3f80,0xbec43f35,0xbf6d3f80,0xbec43f35,0x3ec40000,0x3f6dbf35,0x3f6dbf80,0x3ec4bf35,0xbec40000,0xbf6d3f35,
0xbf6d3f80,0xbec43f35,0x3ec40000,0x3f6dbf35,0x3f6dbf80,0x3ec4bf35,0xbec40000,0xbf6d3f35,0x3f55bf80,0xbe48bec4,0xbf7b3f35,0xbf0e3f6d,
0xbf0e8000,0xbf7b3f6d,0xbe483f35,0x3f55bec4,0xbf553f80,0x3e483ec4,0x3f7bbf35,0x3f0ebf6d,0x3f0e8000,0x3f7bbf6d,0x3e48bf35,0xbf553ec4,
0x3f0e0000,0x3f7bbf6d,0x3e48bf35,0xbf553ec4,0x3f55bf80,0xbe48bec4,0xbf7b3f35,0xbf0e3f6d,0xbf0e0000,0xbf7b3f6d,0xbe483f35,0x3f55bec4,
0xbf553f80,0x3e483ec4,0x3f7bbf35,0x3f0ebf6d,0xbf353f80,0x3f350000,0x3f35bf80,0xbf350000,0xbf353f80,0x3f350000,0x3f35bf80,0xbf350000,
0xbf353f80,0x3f350000,0x3f35bf80,0xbf350000,0xbf353f80,0x3f350000,0x3f35bf80,0xbf350000,0x3f358000,0x3f35bf80,0xbf358000,0xbf353f80,
0x3f358000,0x3f35bf80,0xbf358000,0xbf353f80,0x3f358000,0x3f35bf80,0xbf358000,0xbf353f80,0x3f358000,0x3f35bf80,0xbf358000,0xbf353f80,
0x3f550000,0x3e48bf6d,0xbf7b3f35,0x3f0e3ec4,0xbf0e3f80,0x3f7bbec4,0xbe48bf35,0xbf553f6d,0xbf550000,0xbe483f6d,0x3f7bbf35,0xbf0ebec4,
0x3f0ebf80,0xbf7b3ec4,0x3e483f35,0x3f55bf6d,0x3f0ebf80,0xbf7b3ec4,0x3e483f35,0x3f55bf6d,0x3f558000,0x3e48bf6d,0xbf7b3f35,0x3f0e3ec4,
0xbf0e3f80,0x3f7bbec4,0xbe48bf35,0xbf553f6d,0xbf558000,0xbe483f6d,0x3f7bbf35,0xbf0ebec4,0xbec43f80,0x3f6dbf35,0xbf6d0000,0x3ec43f35,
0x3ec4bf80,0xbf6d3f35,0x3f6d0000,0xbec4bf35,0xbec43f80,0x3f6dbf35,0xbf6d0000,0x3ec43f35,0x3ec4bf80,0xbf6d3f35,0x3f6d0000,0xbec4bf35,
0x3f6d8000,0xbec4bf35,0xbec43f80,0x3f6dbf35,0xbf6d8000,0x3ec43f35,0x3ec4bf80,0xbf6d3f35,0x3f6d8000,0xbec4bf35,0xbec43f80,0x3f6dbf35,
0xbf6d8000,0x3ec43f35,0x3ec4bf80,0xbf6d3f35,0x3f7b0000,0xbf55bec4,0x3f0e3f35,0xbe48bf6d,0x3e48bf80,0xbf0e3f6d,0x3f55bf35,0xbf7b3ec4,
0xbf7b0000,0x3f553ec4,0xbf0ebf35,0x3e483f6d,0xbe483f80,0x3f0ebf6d,0xbf553f35,0x3f7bbec4,0x3e48bf80,0xbf0e3f6d,0x3f55bf35,0xbf7b3ec4,
0xbf7b8000,0x3f553ec4,0xbf0ebf35,0x3e483f6d,0xbe483f80,0x3f0ebf6d,0xbf553f35,0x3f7bbec4,0x3f7b8000,0xbf55bec4,0x3f0e3f35,0xbe48bf6d,
0x3f808000,0xbf808000,0x3f808000,0xbf808000,0x3f808000,0xbf808000,0x3f808000,0xbf808000,0x3f808000,0xbf808000,0x3f808000,0xbf808000,
0x3f808000,0xbf808000,0x3f808000,0xbf808000,0x3f80,0xbf80,0x3f80,0xbf80,0x3f80,0xbf80,0x3f80,0xbf80,
0x3f80,0xbf80,0x3f80,0xbf80,0x3f80,0xbf80,0x3f80,0xbf80,0xbe48bf80,0x3f0e3f6d,0xbf55bf35,0x3f7b3ec4,
0x3f7b8000,0xbf553ec4,0x3f0ebf35,0xbe483f6d,0x3e483f80,0xbf0ebf6d,0x3f553f35,0xbf7bbec4,0xbf7b8000,0x3f55bec4,0xbf0e3f35,0x3e48bf6d,
0x3f7b0000,0xbf553ec4,0x3f0ebf35,0xbe483f6d,0x3e483f80,0xbf0ebf6d,0x3f553f35,0xbf7bbec4,0xbf7b0000,0x3f55bec4,0xbf0e3f35,0x3e48bf6d,
0xbe48bf80,0x3f0e3f6d,0xbf55bf35,0x3f7b3ec4,0x3f6d8000,0xbec43f35,0xbec4bf80,0x3f6d3f35,0xbf6d8000,0x3ec4bf35,0x3ec43f80,0xbf6dbf35,
0x3f6d8000,0xbec43f35,0xbec4bf80,0x3f6d3f35,0xbf6d8000,0x3ec4bf35,0x3ec43f80,0xbf6dbf35,0x3ec43f80,0xbf6dbf35,0x3f6d0000,0xbec43f35,
0xbec4bf80,0x3f6d3f35,0xbf6d0000,0x3ec4bf35,0x3ec43f80,0xbf6dbf35,0x3f6d0000,0xbec43f35,0xbec4bf80,0x3f6d3f35,0xbf6d0000,0x3ec4bf35,
0xbf0ebf80,0x3f7b3ec4,0xbe483f35,0xbf55bf6d,0xbf558000,0xbe48bf6d,0x3f7b3f35,0xbf0e3ec4,0x3f0e3f80,0xbf7bbec4,0x3e48bf35,0x3f553f6d,
0x3f558000,0x3e483f6d,0xbf7bbf35,0x3f0ebec4,0x3f550000,0x3e483f6d,0xbf7bbf35,0x3f0ebec4,0xbf0ebf80,0x3f7b3ec4,0xbe483f35,0xbf55bf6d,
0xbf550000,0xbe48bf6d,0x3f7b3f35,0xbf0e3ec4,0x3f0e3f80,0xbf7bbec4,0x3e48bf35,0x3f553f6d,0x3f353f80,0xbf350000,0xbf35bf80,0x3f350000,
0x3f353f80,0xbf350000,0xbf35bf80,0x3f350000,0x3f353f80,0xbf350000,0xbf35bf80,0x3f350000,0x3f353f80,0xbf350000,0xbf35bf80,0x3f350000,
0x3f358000,0x3f353f80,0xbf358000,0xbf35bf80,0x3f358000,0x3f353f80,0xbf358000,0xbf35bf80,0x3f358000,0x3f353f80,0xbf358000,0xbf35bf80,
0x3f358000,0x3f353f80,0xbf358000,0xbf35bf80,0x3f0e0000,0x3f7b3f6d,0x3e483f35,0xbf55bec4,0x3f553f80,0xbe483ec4,0xbf7bbf35,0xbf0ebf6d,
0xbf0e0000,0xbf7bbf6d,0xbe48bf35,0x3f553ec4,0xbf55bf80,0x3e48bec4,0x3f7b3f35,0x3f0e3f6d,0xbf55bf80,0x3e48bec4,0x3f7b3f35,0x3f0e3f6d,
0x3f0e8000,0x3f7b3f6d,0x3e483f35,0xbf55bec4,0x3f553f80,0xbe483ec4,0xbf7bbf35,0xbf0ebf6d,0xbf0e8000,0xbf7bbf6d,0xbe48bf35,0x3f553ec4,
0x3f6d3f80,0x3ec43f35,0xbec40000,0xbf6dbf35,0xbf6dbf80,0xbec4bf35,0x3ec40000,0x3f6d3f35,0x3f6d3f80,0x3ec43f35,0xbec40000,0xbf6dbf35,
0xbf6dbf80,0xbec4bf35,0x3ec40000,0x3f6d3f35,0x3ec48000,0x3f6d3f35,0x3f6d3f80,0x3ec43f35,0xbec48000,0xbf6dbf35,0xbf6dbf80,0xbec4bf35,
0x3ec48000,0x3f6d3f35,0x3f6d3f80,0x3ec43f35,0xbec48000,0xbf6dbf35,0xbf6dbf80,0xbec4bf35,0x3e480000,0x3f0e3ec4,0x3f553f35,0x3f7b3f6d,
0xbf7bbf80,0xbf55bf6d,0xbf0ebf35,0xbe48bec4,0xbe480000,0xbf0ebec4,0xbf55bf35,0xbf7bbf6d,0x3f7b3f80,0x3f553f6d,0x3f0e3f35,0x3e483ec4,
0xbf7bbf80,0xbf55bf6d,0xbf0ebf35,0xbe48bec4,0xbe488000,0xbf0ebec4,0xbf55bf35,0xbf7bbf6d,0x3f7b3f80,0x3f553f6d,0x3f0e3f35,0x3e483ec4,
0x3e488000,0x3f0e3ec4,0x3f553f35,0x3f7b3f6d,0x3f803f80,0x80008000,0x3f803f80,0x80008000,0x3f803f80,0x80008000,0x3f803f80,0x80008000,
0x3f803f80,0x80008000,0x3f803f80,0x80008000,0x3f803f80,0x80008000,0x3f803f80,0x80008000,0x3f803f80,0xbbc98000,0x3f803f80,0xbd62bd49,
0x3f803f80,0xbc97bc49,0x3f7f3f80,0xbd8abd7b,0x3f803f80,0xbcfbbcc9,0x3f7f3f7f,0xbda3bd97,0x3f803f80,0xbd30bd17,0x3f7f3f7f,0xbdbcbdb0,
0x3f803f80,0xbc498000,0x3f7e3f7f,0xbde2bdc9,0x3f803f80,0xbd17bcc9,0x3f7e3f7e,0xbe0abdfb,0x3f803f80,0xbd7bbd49,0x3f7d3f7d,0xbe23be16,
0x3f7f3f7f,0xbdb0bd97,0x3f7c3f7c,0xbe3bbe2f,0x3f803f80,0xbc978000,0x3f7c3f7d,0xbe29be16,0x3f803f80,0xbd62bd17,0x3f7b3f7c,0xbe4ebe3b,
0x3f7f3f7f,0xbdbcbd97,0x3f793f7a,0xbe73be60,0x3f7e3f7e,0xbe04bde2,0x3f763f78,0xbe8cbe82,0x3f803f80,0xbcc98000,0x3f7a3f7b,0xbe60be48,
0x3f7f3f80,0xbd97bd49,0x3f773f78,0xbe89be79,0x3f7e3f7f,0xbdfbbdc9,0x3f733f75,0xbea1be95,0x3f7c3f7d,0xbe2fbe16,0x3f6f3f71,0xbeb8beac,
0x3f803f80,0xbcfb8000,0x3f763f78,0xbe8cbe79,0x3f7f3f80,0xbdbcbd7b,0x3f723f74,0xbeaabe9b,0x3f7d3f7e,0xbe1cbdfb,0x3f6c3f6f,0xbec7beb8,
0x3f7a3f7c,0xbe5abe3b,0x3f653f69,0xbee3bed5,0x3f803f80,0xbd178000,0x3f723f75,0xbea7be95,0x3f7e3f7f,0xbde2bd97,0x3f6b3f6f,0xbecabeb8,
0x3f7c3f7d,0xbe3bbe16,0x3f633f67,0xbeecbedb,0x3f783f7a,0xbe82be60,0x3f5a3f5f,0xbf06befc,0x3f803f80,0xbd308000,0x3f6d3f71,0xbec1beac,
0x3f7e3f7f,0xbe04bdb0,0x3f643f69,0xbee9bed5,0x3f7a3f7c,0xbe5abe2f,0x3f593f5f,0xbf08befc,0x3f753f78,0xbe98be82,0x3f4d3f53,0xbf1abf11,
0x3f803f80,0x80008000,0x3f803f80,0x80008000,0x3f803f80,0x80008000,0x3f803f80,0x80008000,0x3f803f80,0x80008000,0x3f803f80,0x80008000,
0x3f803f80,0x80008000,0x3f803f80,0x80008000,0x3f7f3f7f,0xbdd5bdc9,0x3f7d3f7d,0xbe1cbe16,0x3f7e3f7e,0xbdeebde2,0x3f7c3f7d,0xbe29be23,
0x3f7e3f7e,0xbe04bdfb,0x3f7c3f7c,0xbe35be2f,0x3f7d3f7e,0xbe10be0a,0x3f7b3f7c,0xbe42be3b,0x3f7a3f7b,0xbe54be48,0x3f743f75,0xbe9bbe95,
0x3f793f7a,0xbe6dbe60,0x3f723f73,0xbea7bea1,0x3f783f78,0xbe82be79,0x3f703f71,0xbeb2beac,0x3f763f77,0xbe8fbe89,0x3f6e3f6f,0xbebebeb8,
0x3f743f75,0xbe9ebe95,0x3f653f67,0xbee3bedb,0x3f713f72,0xbeafbea7,0x3f613f63,0xbef4beec,0x3f6d3f6f,0xbec1beb8,0x3f5c3f5f,0xbf02befc,
0x3f693f6b,0xbed2beca,0x3f573f5a,0xbf0abf06,0x3f6a3f6d,0xbecfbec4,0x3f513f55,0xbf13bf0e,0x3f653f67,0xbee6bedb,0x3f4a3f4e,0xbf1dbf18,
0x3f5f3f62,0xbefcbef1,0x3f423f46,0xbf27bf22,0x3f583f5c,0xbf09bf04,0x3f393f3e,0xbf31bf2c,0x3f5e3f62,0xbeffbef1,0x3f383f3e,0xbf32bf2c,
0x3f563f5a,0xbf0dbf06,0x3f2d3f33,0xbf3dbf37,0x3f4d3f51,0xbf1abf13,0x3f213f27,0xbf47bf42,0x3f433f48,0xbf26bf20,0x3f153f1b,0xbf50bf4c,
0x3f4f3f55,0xbf16bf0e,0x3f1b3f22,0xbf4cbf46,0x3f443f4a,0xbf25bf1d,0x3f0c3f13,0xbf57bf51,0x3f373f3e,0xbf33bf2c,0x3ef73f04,0xbf60bf5c,
0x3f2a3f31,0xbf40bf39,0x3ed53ee6,0xbf69bf65,0x3f3f3f46,0xbf2bbf22,0x3ef43f04,0xbf61bf5c,0x3f2f3f37,0xbf3abf33,0x3ecd3ee1,0xbf6bbf66,
0x3f1f3f27,0xbf49bf42,0x3ea43eb8,0xbf73bf6f,0x3f0d3f16,0xbf56bf4f,0x3e733e8f,0xbf79bf76,0x3f803f80,0xbd498000,0x3f673f6d,0xbedbbec4,
0x3f7d3f7f,0xbe16bdc9,0x3f5c3f62,0xbf04bef1,0x3f783f7b,0xbe79be48,0x3f4e3f55,0xbf18bf0e,0x3f713f75,0xbeacbe95,0x3f3e3f46,0xbf2cbf22,
0x3f803f80,0xbd628000,0x3f613f67,0xbef4bedb,0x3f7c3f7e,0xbe29bde2,0x3f523f5a,0xbf12bf06,0x3f763f7a,0xbe8cbe60,0x3f413f4a,0xbf28bf1d,
0x3f6d3f72,0xbec1bea7,0x3f2d3f37,0xbf3dbf33,0x3f803f80,0xbd7b8000,0x3f5a3f62,0xbf06bef1,0x3f7c3f7e,0xbe3bbdfb,0x3f483f51,0xbf20bf13,
0x3f743f78,0xbe9bbe79,0x3f333f3e,0xbf37bf2c,0x3f693f6f,0xbed5beb8,0x3f1b3f27,0xbf4cbf42,0x3f7f3f80,0xbd8a8000,0x3f523f5c,0xbf12bf04,
0x3f7b3f7e,0xbe4ebe0a,0x3f3d3f48,0xbf2dbf20,0x3f723f77,0xbeaabe89,0x3f243f31,0xbf45bf39,0x3f643f6b,0xbee9beca,0x3f083f16,0xbf59bf4f,
0x3f7f3f80,0xbd978000,0x3f4a3f55,0xbf1dbf0e,0x3f7a3f7d,0xbe60be16,0x3f313f3e,0xbf39bf2c,0x3f6f3f75,0xbeb8be95,0x3f133f22,0xbf51bf46,
0x3f5f3f67,0xbefcbedb,0x3ee63f04,0xbf65bf5c,0x3f7f3f80,0xbda38000,0x3f413f4e,0xbf28bf18,0x3f793f7d,0xbe73be23,0x3f243f33,0xbf45bf37,
0x3f6c3f73,0xbec7bea1,0x3f023f13,0xbf5cbf51,0x3f593f63,0xbf08beec,0x3ebb3ee1,0xbf6ebf66,0x3f7f3f80,0xbdb08000,0x3f373f46,0xbf33bf22,
0x3f783f7c,0xbe82be2f,0x3f163f27,0xbf4fbf42,0x3f693f71,0xbed5beac,0x3ee13f04,0xbf66bf5c,0x3f533f5f,0xbf11befc,0x3e8f3eb8,0xbf76bf6f,
0x3f7f3f80,0xbdbc8000,0x3f2d3f3e,0xbf3dbf2c,0x3f763f7c,0xbe8cbe3b,0x3f083f1b,0xbf59bf4c,0x3f653f6f,0xbee3beb8,0x3ebb3ee6,0xbf6ebf65,
0x3f4d3f5a,0xbf1abf06,0x3e423e8f,0xbf7bbf76,0x3f2c3f35,0xbf3ebf35,0x3eac3ec4,0xbf71bf6d,0x3f183f22,0xbf4ebf46,0x3e793e95,0xbf78bf75,
0x3f043f0e,0xbf5cbf55,0x3e163e48,0xbf7dbf7b,0x3edb3ef1,0xbf67bf62,0x3d493dc9,0xbf80bf7f,0x3f173f22,0xbf4fbf46,0x3e423e79,0xbf7bbf78,
0x3eff3f0c,0xbf5ebf57,0x3da33e0a,0xbf7fbf7e,0x3ecd3ee6,0xbf6bbf65,0xbcfb3cc9,0xbf80bf80,0x3e983eb2,0xbf75bf70,0xbe10bdb0,0xbf7dbf7f,
0x3f013f0e,0xbf5dbf55,0x3d173dc9,0xbf80bf7f,0x3eca3ee6,0xbf6bbf65,0xbdb0bcc9,0xbf7fbf80,0x3e8f3eac,0xbf76bf71,0xbe54be16,0xbf7abf7d,
0x3e233e60,0xbf7dbf7a,0xbea7be89,0xbf72bf77,0x3ed23ef1,0xbf69bf62,0xbdeebd49,0xbf7ebf80,0x3e923eb2,0xbf75bf70,0xbe7fbe3b,0xbf78bf7c,
0x3e1c3e60,0xbf7dbf7a,0xbec1bea1,0xbf6dbf73,0x3c973db0,0xbf80bf7f,0xbeffbee1,0xbf5ebf66,0x3ea13ec4,0xbf73bf6d,0xbe89be48,0xbf77bf7b,
0x3e2f3e79,0xbf7cbf78,0xbecfbeac,0xbf6abf71,0x3cc93dc9,0xbf80bf7f,0xbf09bef1,0xbf58bf62,0xbdfbbd49,0xbf7ebf80,0xbf27bf18,0xbf42bf4e,
0x3e5a3e95,0xbf7abf75,0xbed2beac,0xbf69bf71,0x3d623e0a,0xbf80bf7e,0xbf0dbef7,0xbf56bf60,0xbdd5bcc9,0xbf7fbf80,0xbf2dbf1d,0xbf3dbf4a,
0xbe86be3b,0xbf77bf7c,0xbf49bf3c,0xbf1fbf2e,0x3de23e48,0xbf7ebf7b,0xbf0cbef1,0xbf57bf62,0xbd7b3cc9,0xbf80bf80,0xbf2ebf1d,0xbf3cbf4a,
0xbe6dbe16,0xbf79bf7d,0xbf4cbf3e,0xbf1bbf2c,0xbecabea1,0xbf6bbf73,0xbf63bf58,0xbeecbf09,0x3bc93dc9,0xbf80bf7f,0xbf2bbf18,0xbf3fbf4e,
0xbe35bdb0,0xbf7cbf7f,0xbf4bbf3c,0xbf1cbf2e,0xbeb5be89,0xbf6fbf77,0xbf64bf58,0xbee9bf09,0xbf05bee1,0xbf5bbf66,0xbf75bf6e,0xbe92bebe,
0x3f7f3f80,0xbdc98000,0x3f223f35,0xbf46bf35,0x3f753f7b,0xbe95be48,0x3ef13f0e,0xbf62bf55,0x3f623f6d,0xbef1bec4,0x3e953ec4,0xbf75bf6d,
0x3f463f55,0xbf22bf0e,0x3dc93e48,0xbf7fbf7b,0x3f7f3f80,0xbdd58000,0x3f173f2c,0xbf4fbf3e,0x3f743f7a,0xbe9ebe54,0x3ed23f01,0xbf69bf5d,
0x3f5e3f6a,0xbeffbecf,0x3e5a3ea1,0xbf7abf73,0x3f3f3f4f,0xbf2bbf16,0x3bc93de2,0xbf80bf7e,0x3f7e3f80,0xbde28000,0x3f0c3f22,0xbf57bf46,
0x3f723f7a,0xbea7be60,0x3eb23ee6,0xbf70bf65,0x3f5a3f67,0xbf06bedb,0x3e0a3e79,0xbf7ebf78,0x3f373f4a,0xbf33bf1d,0xbdb03cc9,0xbf7fbf80,
0x3f7e3f80,0xbdee8000,0x3eff3f18,0xbf5ebf4e,0x3f713f79,0xbeafbe6d,0x3e923eca,0xbf75bf6b,0x3f563f65,0xbf0dbee6,0x3d623e2f,0xbf80bf7c,
0x3f2f3f44,0xbf3abf25,0xbe35bd7b,0xbf7cbf80,0x3f7e3f80,0xbdfb8000,0x3ee63f0e,0xbf65bf55,0x3f6f3f78,0xbeb8be79,0x3e603eac,0xbf7abf71,
0x3f513f62,0xbf13bef1,0xbcc93dc9,0xbf80bf7f,0x3f273f3e,0xbf42bf2c,0xbe89be16,0xbf77bf7d,0x3f7e3f80,0xbe048000,0x3ecd3f04,0xbf6bbf5c,
0x3f6d3f78,0xbec1be82,0x3e1c3e8f,0xbf7dbf76,0x3f4d3f5f,0xbf1abefc,0xbdd53cc9,0xbf7fbf80,0x3f1f3f37,0xbf49bf33,0xbeb5be6d,0xbf6fbf79,
0x3f7e3f80,0xbe0a8000,0x3eb23ef1,0xbf70bf62,0x3f6b3f77,0xbecabe89,0x3db03e60,0xbf7fbf7a,0x3f483f5c,0xbf20bf04,0xbe3bbd49,0xbf7cbf80,
0x3f163f31,0xbf4fbf39,0xbee1bea1,0xbf66bf73,0x3f7d3f80,0xbe108000,0x3e983edb,0xbf75bf67,0x3f693f76,0xbed2be8f,0x3c973e23,0xbf80bf7d,
0x3f433f58,0xbf26bf09,0xbe86bdfb,0xbf77bf7e,0x3f0d3f2a,0xbf56bf40,0xbf05beca,0xbf5bbf6b,0xbdc90000,0xbf7fbf80,0xbf46bf35,0xbf22bf35,
0xbe95be48,0xbf75bf7b,0xbf62bf55,0xbef1bf0e,0xbef1bec4,0xbf62bf6d,0xbf75bf6d,0xbe95bec4,0xbf22bf0e,0xbf46bf55,0xbf7fbf7b,0xbdc9be48,
0xbe4ebdc9,0xbf7bbf7f,0xbf5cbf4e,0xbf02bf18,0xbecdbe9b,0xbf6bbf74,0xbf73bf69,0xbea4bed5,0xbf15befc,0xbf50bf5f,0xbf7ebf7a,0xbdeebe60,
0xbf3dbf2a,0xbf2dbf40,0xbf7fbf80,0x3dbcbc49,0xbe9bbe48,0xbf74bf7b,0xbf6ebf62,0xbebebef1,0xbf01becf,0xbf5dbf6a,0xbf7dbf77,0xbe23be89,
0xbf2ebf18,0xbf3cbf4e,0xbf80bf80,0x3d7bbd49,0xbf53bf42,0xbf11bf27,0xbf76bf7c,0x3e8f3e2f,0xbecdbe95,0xbf6bbf75,0xbf79bf71,0xbe66beac,
0xbf1abf01,0xbf4dbf5d,0xbf80bf7e,0x3bc9bde2,0xbf45bf31,0xbf24bf39,0xbf79bf7e,0x3e733dfb,0xbf65bf57,0xbee3bf0c,0xbf64bf70,0x3ee93eb2,
0xbefcbec4,0xbf5fbf6d,0xbf7fbf7b,0xbd97be48,0xbf31bf18,0xbf39bf4e,0xbf7cbf80,0x3e2f3d49,0xbf58bf46,0xbf09bf22,0xbf6abf75,0x3ecf3e95,
0xbf73bf67,0xbea1bedb,0xbf4abf5c,0x3f1d3f04,0xbf15bef1,0xbf50bf62,0xbf7fbf80,0x3da3bd49,0xbf45bf2e,0xbf24bf3c,0xbf72bf7a,0x3eaa3e54,
0xbf68bf58,0xbed8bf09,0xbf54bf65,0x3f103ee6,0xbf7cbf74,0xbe35be9b,0xbf28bf40,0x3f413f2a,0xbf2abf0e,0xbf40bf55,0xbf79bf7f,0x3e6d3dc9,
0xbf57bf42,0xbf0cbf27,0xbf60bf6f,0x3ef73eb8,0xbf74bf67,0xbe9bbedb,0xbf37bf4e,0x3f333f18,0xbf80bf7c,0xbd17be2f,0xbf01bf1d,0x3f5d3f4a,
0xbf3dbf22,0xbf2dbf46,0xbf6dbf78,0x3ec13e79,0xbf65bf53,0xbee3bf11,0xbf49bf5d,0x3f1f3f01,0xbf7cbf73,0xbe35bea1,0xbf15bf31,0x3f503f39,
0xbf7fbf80,0x3dd5bd17,0xbeaabeec,0x3f723f63,0x3f7d3f80,0xbe168000,0x3e793ec4,0xbf78bf6d,0x3f673f75,0xbedbbe95,0xbd493dc9,0xbf80bf7f,
0x3f3e3f55,0xbf2cbf0e,0xbeacbe48,0xbf71bf7b,0x3f043f22,0xbf5cbf46,0xbf18bef1,0xbf4ebf62,0x3f7d3f80,0xbe1c8000,0x3e423eac,0xbf7bbf71,
0x3f653f74,0xbee3be9b,0xbdee3d17,0xbf7ebf80,0x3f383f51,0xbf32bf13,0xbed2be89,0xbf69bf77,0x3ef43f1b,0xbf61bf4c,0xbf2bbf0c,0xbf3fbf57,
0x3f7d3f80,0xbe238000,0x3e0a3e95,0xbf7ebf75,0x3f633f73,0xbeecbea1,0xbe3bbcc9,0xbf7cbf80,0x3f333f4e,0xbf37bf18,0xbef7beac,0xbf60bf71,
0x3ee13f13,0xbf66bf51,0xbf3cbf1d,0xbf2ebf4a,0x3f7c3f80,0xbe298000,0x3da33e79,0xbf7fbf78,0x3f613f72,0xbef4bea7,0xbe7fbdb0,0xbf78bf7f,
0x3f2d3f4a,0xbf3dbf1d,0xbf0dbecf,0xbf56bf6a,0x3ecd3f0c,0xbf6bbf57,0xbf4bbf2e,0xbf1cbf3c,0x3f7c3f80,0xbe2f8000,0x3cc93e48,0xbf80bf7b,
0x3f5f3f71,0xbefcbeac,0xbea1be16,0xbf73bf7d,0x3f273f46,0xbf42bf22,0xbf1dbef1,0xbf4abf62,0x3eb83f04,0xbf6fbf5c,0xbf58bf3e,0xbf09bf2c,
0x3f7c3f80,0xbe358000,0xbcfb3e16,0xbf80bf7d,0x3f5c3f70,0xbf02beb2,0xbec1be54,0xbf6dbf7a,0x3f213f42,0xbf47bf27,0xbf2dbf09,0xbf3dbf58,
0x3ea43ef7,0xbf73bf60,0xbf64bf4c,0xbee9bf1b,0x3f7c3f80,0xbe3b8000,0xbdb03dc9,0xbf7fbf7f,0x3f5a3f6f,0xbf06beb8,0xbee1be89,0xbf66bf77,
0x3f1b3f3e,0xbf4cbf2c,0xbf3cbf18,0xbf2ebf4e,0x3e8f3ee6,0xbf76bf65,0xbf6ebf58,0xbebebf09,0x3f7b3f80,0xbe428000,0xbe103d49,0xbf7dbf80,
0x3f573f6e,0xbf0abebe,0xbeffbea7,0xbf5ebf72,0x3f153f39,0xbf50bf31,0xbf49bf27,0xbf1fbf42,0x3e733ed5,0xbf79bf69,0xbf75bf63,0xbe92beec,
0xbf4ebf35,0xbf18bf35,0xbf5cbf6d,0x3f043ec4,0xbf71bf62,0xbeacbef1,0xbf2cbf46,0x3f3e3f22,0xbf80bf7b,0xbd49be48,0xbedbbf0e,0x3f673f55,
0xbf78bf7f,0x3e793dc9,0xbe16be95,0x3f7d3f75,0xbf5cbf46,0xbf02bf22,0xbf45bf5c,0x3f243f04,0xbf79bf6e,0xbe66bebe,0xbf0abf2a,0x3f573f40,
0xbf7fbf7f,0x3da3bd97,0xbe86becf,0x3f773f6a,0xbf6dbf79,0x3ec13e6d,0x3d30bde2,0x3f803f7e,0xbf69bf55,0xbed5bf0e,0xbf2abf46,0x3f403f22,
0xbf7ebf77,0xbde2be89,0xbecabf09,0x3f6b3f58,0xbf7abf80,0x3e543d49,0xbdb0be79,0x3f7f3f78,0xbf5dbf6f,0x3f013eb8,0x3e6d3d97,0x3f793f7f,
0xbf73bf62,0xbea4bef1,0xbf0abf2c,0x3f573f3e,0xbf80bf7d,0x3bc9be23,0xbe73beca,0x3f793f6b,0xbf72bf7c,0x3eaa3e2f,0x3dbcbd97,0x3f7f3f7f,
0xbf49bf60,0x3f1f3ef7,0x3ed23e82,0x3f693f78,0xbf7abf6d,0xbe60bec4,0xbecfbf0e,0x3f6a3f55,0xbf7ebf80,0x3dfbbd49,0xbd97be79,0x3f7f3f78,
0xbf65bf75,0x3ee63e95,0x3e893dc9,0x3f773f7f,0xbf31bf4e,0x3f393f18,0x3f133edb,0x3f513f67,0xbf7ebf75,0xbdeebe95,0xbe86bedb,0x3f773f67,
0xbf79bf80,0x3e733d7b,0x3dbcbdb0,0x3f7f3f7f,0xbf54bf6a,0x3f103ecf,0x3ede3e89,0x3f673f77,0xbf15bf37,0x3f503f33,0x3f383f16,0x3f323f4f,
0xbf80bf7b,0xbc49be48,0xbde2be95,0x3f7e3f75,0xbf70bf7c,0x3eb23e2f,0x3e823d97,0x3f783f7f,0xbf40bf5c,0x3f2a3f04,0x3f163edb,0x3f4f3f67,
0xbeecbf1d,0x3f633f4a,0x3f573f39,0x3f0c3f31,0xbf7fbf7f,0x3dbcbdc9,0x3d30be16,0x3f803f7d,0xbf64bf76,0x3ee93e8f,0x3ed23e6d,0x3f693f79,
0xbf28bf4a,0x3f413f1d,0x3f383f13,0x3f323f51,0xbeaabf01,0x3f723f5d,0x3f6d3f57,0x3ec13f0c,
};
__device__ const __align__(128) uint64_t c_inv[16384] = {
0x3f003f003f003f00,0x3f003f003f003f00,0x3f003f003f003f00,0x3f003f003f003f00,0x3f003f003f003f00,0x3f003f003f003f00,0x3f003f003f003f00,0x3f003f003f003f00,
0xbf003f00bf003f00,0xbf003f00bf003f00,0xbf003f00bf003f00,0xbf003f00bf003f00,0xbf003f00bf003f00,0xbf003f00bf003f00,0xbf003f00bf003f00,0xbf003f00bf003f00,
0x3f773f783f7a3f7b,0x3f6f3f713f733f75,0x3f7f3f803f803f80,0x3f7c3f7d3f7e3f7f,0x3f4a3f4e3f513f55,0x3f393f3e3f423f46,0x3f653f673f6a3f6d,0x3f583f5c3f5f3f62,
0xbe89be79be60be48,0xbeb8beacbea1be95,0xbd97bd49bcc98000,0xbe2fbe16bdfbbdc9,0xbf1dbf18bf13bf0e,0xbf31bf2cbf27bf22,0xbee6bedbbecfbec4,0xbf09bf04befcbef1,
0x3f183f223f2c3f35,0x3edb3ef13f043f0e,0x3e793e953eac3ec4,0x3d493dc93e163e48,0x3f7d3f7f3f803f80,0x3f713f753f783f7b,0x3f5c3f623f673f6d,0x3f3e3f463f4e3f55,
0xbf4ebf46bf3ebf35,0xbf67bf62bf5cbf55,0xbf78bf75bf71bf6d,0xbf80bf7fbf7dbf7b,0xbe16bdc9bd498000,0xbeacbe95be79be48,0xbf04bef1bedbbec4,0xbf2cbf22bf18bf0e,
0xbecfbeacbe89be48,0xbf27bf18bf09bef1,0x3e2f3e793ea13ec4,0xbdfbbd493cc93dc9,0x3f313f3e3f4a3f55,0x3ee63f043f133f22,0x3f7a3f7d3f7f3f80,0x3f5f3f673f6f3f75,
0xbf6abf71bf77bf7b,0xbf42bf4ebf58bf62,0xbf7cbf78bf73bf6d,0xbf7ebf80bf80bf7f,0xbf39bf2cbf1dbf0e,0xbf65bf5cbf51bf46,0xbe60be16bd978000,0xbefcbedbbeb8be95,
0x3f753f7b3f7f3f80,0x3f463f553f623f6d,0x3ef13f0e3f223f35,0x3dc93e483e953ec4,0xbe95be48bdc90000,0xbf22bf0ebef1bec4,0xbf62bf55bf46bf35,0xbf7fbf7bbf75bf6d,
0xbe95be48bdc98000,0xbf22bf0ebef1bec4,0xbf62bf55bf46bf35,0xbf7fbf7bbf75bf6d,0xbf75bf7bbf7fbf80,0xbf46bf55bf62bf6d,0xbef1bf0ebf22bf35,0xbdc9be48be95bec4,
0x3e603eac3ee63f0e,0xbe89be16bcc93dc9,0x3f6f3f783f7e3f80,0x3f273f3e3f513f62,0xbf7cbf80bf7fbf7b,0xbf4abf5cbf6abf75,0xbf31bf18befcbec4,0xbf73bf67bf58bf46,
0xbf7abf71bf65bf55,0xbf77bf7dbf80bf7f,0xbeb8be79bdfb8000,0xbf42bf2cbf13bef1,0x3e2f3d49bd97be48,0x3f1d3f043ecf3e95,0xbf39bf4ebf5fbf6d,0xbea1bedbbf09bf22,
0xbf71bf62bf4ebf35,0xbf78bf7fbf80bf7b,0xbf2cbf46bf5cbf6d,0xbe16be95bedbbf0e,0x3f673f753f7d3f80,0x3f043f223f3e3f55,0xbd493dc93e793ec4,0xbf18bef1beacbe48,
0xbeacbef1bf18bf35,0x3e793dc9bd49be48,0x3f3e3f223f043ec4,0x3f7d3f753f673f55,0xbedbbe95be168000,0xbf5cbf46bf2cbf0e,0xbf80bf7fbf78bf6d,0xbf4ebf62bf71bf7b,
0xbd97be79becfbf0e,0x3f133edb3e893dc9,0xbf7ebf80bf7abf6d,0xbf31bf4ebf65bf75,0xbea1be163cc93e48,0xbf58bf3ebf1dbef1,0x3f5f3f713f7c3f80,0x3eb83f043f273f46,
0x3f7f3f783f6a3f55,0x3f513f673f773f7f,0x3dfbbd49be60bec4,0x3f393f183ee63e95,0xbf73bf7dbf80bf7b,0xbf09bf2cbf4abf62,0xbefcbeacbe2f8000,0xbf6fbf5cbf42bf22,
0x3f553f6d3f7b3f80,0x3e483ec43f0e3f35,0xbf0ebec4be480000,0xbf7bbf6dbf55bf35,0xbf55bf6dbf7bbf80,0xbe48bec4bf0ebf35,0x3f0e3ec43e480000,0x3f7b3f6d3f553f35,
0xbf0ebec4be488000,0xbf7bbf6dbf55bf35,0xbf55bf6dbf7bbf80,0xbe48bec4bf0ebf35,0x3f0e3ec43e488000,0x3f7b3f6d3f553f35,0x3f553f6d3f7b3f80,0x3e483ec43f0e3f35,
0xbf42bf18becfbe48,0xbf7cbf80bf77bf62,0x3f4a3f673f7a3f80,0x3cc93e793ee63f22,0x3f733f5c3f393f0e,0x3f583f713f7e3f7f,0xbefcbf2cbf51bf6d,0x3eb83e16bd97be95,
0xbf27bf4ebf6abf7b,0x3e2fbd49be89bef1,0xbf1dbedbbe608000,0xbf80bf78bf65bf46,0x3ea13f043f313f55,0xbf09beacbdfb3dc9,0x3f5f3f3e3f133ec4,0x3f6f3f7d3f7f3f75,
0xbd49be95bf04bf35,0x3f4e3f223edb3e48,0x3f713f7f3f7d3f6d,0x3e793ef13f2c3f55,0x3f3e3f623f783f80,0xbe163dc93eac3f0e,0xbf67bf46bf18bec4,0xbf5cbf75bf80bf7b,
0x3f803f753f5c3f35,0x3f183f463f673f7b,0xbeacbdc93e163ec4,0xbf78bf62bf3ebf0e,0xbf2cbef1be798000,0xbf7dbf7fbf71bf55,0xbedbbf22bf4ebf6d,0x3f043e953d49be48,
0x3f093f3e3f653f7b,0xbefcbe793cc93e95,0x3ecf3e16bdfbbec4,0x3f7f3f713f513f22,0xbf7cbf67bf42bf0e,0xbf1dbf4ebf6fbf7f,0x3f313f5c3f773f80,0xbea1bd493e603ef1,
0xbf58bf2cbee6be48,0xbf5fbf78bf80bf75,0x3f6a3f7d3f7e3f6d,0x3d973eac3f133f46,0xbe2fbedbbf27bf55,0x3f4a3f183eb83dc9,0xbf39bf04be898000,0xbf73bf80bf7abf62,
0x3f223f553f753f80,0xbef1be483dc93ec4,0xbf7fbf7bbf62bf35,0xbe95bf0ebf46bf6d,0x3f463f0e3e950000,0x3f623f7b3f7f3f6d,0xbdc93e483ef13f35,0xbf75bf55bf22bec4,
0xbf46bf0ebe958000,0xbf62bf7bbf7fbf6d,0x3dc9be48bef1bf35,0x3f753f553f223ec4,0x3f223f553f753f80,0xbef1be483dc93ec4,0xbf7fbf7bbf62bf35,0xbe95bf0ebf46bf6d,
0xbf6fbf80bf77bf55,0x3d97be79bf09bf46,0x3f133f4e3f733f80,0xbf1dbeacbcc93e95,0xbf31bedbbdfb3e48,0xbf65bf7dbf7cbf62,0x3f7a3f5c3f273ec4,0x3efc3f3e3f6a3f7f,
0x3eb83d49be89bf0e,0x3f7f3f783f583f22,0xbf51bf18bea18000,0xbf4abf71bf80bf75,0xbf39bf67bf7ebf7b,0x3ee63e16be2fbef1,0x3e603f043f423f6d,0xbf5fbf2cbecfbdc9,
0x3f783f7f3f673f35,0xbd493e953f183f55,0xbf7dbf62bf2cbec4,0xbeacbf22bf5cbf7b,0x3f043f463f713f80,0xbf3ebef1be163e48,0xbf4ebf75bf80bf6d,0x3edb3dc9be79bf0e,
0xbe793dc93edb3f35,0xbf80bf75bf4ebf0e,0xbe16bef1bf3ebf6d,0x3f713f463f043e48,0xbf5cbf22beac8000,0xbf2cbf62bf7dbf7b,0x3f183e95bd49bec4,0x3f673f7f3f783f55,
0xbf5fbf7dbf7abf55,0x3ecf3d49bea1bf22,0x3f423f713f803f6d,0xbf13be793dfb3ef1,0xbf1dbf5cbf7cbf7b,0x3f393edb3d97be95,0x3ee63f3e3f6f3f80,0xbf58bf18be893dc9,
0x3efc3e16be60bf0e,0x3f6a3f803f733f46,0xbf27beac3cc93ec4,0xbf51bf78bf7ebf62,0x3f4a3f043e2fbe48,0x3f313f673f7f3f75,0xbf65bf2cbeb88000,0xbf09bf4ebf77bf7f,
0x3ec43f353f6d3f80,0xbf6dbf35bec40000,0xbec4bf35bf6dbf80,0x3f6d3f353ec40000,0x3ec43f353f6d3f80,0xbf6dbf35bec40000,0xbec4bf35bf6dbf80,0x3f6d3f353ec40000,
0xbf6dbf35bec48000,0xbec4bf35bf6dbf80,0x3f6d3f353ec48000,0x3ec43f353f6d3f80,0xbf6dbf35bec48000,0xbec4bf35bf6dbf80,0x3f6d3f353ec48000,0x3ec43f353f6d3f80,
0xbdfbbf04bf51bf7b,0x3f803f673f273e95,0x3ea13f2c3f6a3f80,0xbf7abf4ebefcbdc9,0x3e89be16bf09bf55,0x3f6f3f803f653f22,0xbd973eac3f313f6d,0xbf7cbf78bf4abef1,
0x3f7e3f5c3f133e48,0x3cc93edb3f423f75,0xbf73bf3ebecf8000,0xbe60bf18bf5fbf7f,0x3f773f7d3f583f0e,0xbeb83d493ee63f46,0xbf7fbf71bf39bec4,0x3e2fbe79bf1dbf62,
0xbf04bdc93eac3f35,0xbf3ebf75bf7dbf55,0x3f4e3ef13d49bec4,0x3edb3f463f783f7b,0x3e793f223f673f80,0xbf80bf62bf18be48,0x3e16be95bf2cbf6d,0x3f713f7f3f5c3f0e,
0xbf5cbf7fbf71bf35,0x3f2c3e95be16bf0e,0x3f183f623f803f6d,0xbf67bf22be793e48,0xbf78bf46bedb8000,0xbd49bef1bf4ebf7b,0x3f7d3f753f3e3ec4,0xbeac3dc93f043f55,
0x3f803f673f1d3e48,0xbea13e163f133f62,0xbf58bf04bd973ec4,0xbe89bf2cbf6fbf7f,0x3ecfbd49befcbf55,0x3f423f783f7a3f46,0x3e2f3f183f653f80,0xbf7ebf71bf31be95,
0xbcc93edb3f4a3f7b,0xbf73bf7dbf51bef1,0xbf09bf5cbf7fbf6d,0x3f773f3e3eb8bdc9,0x3f6a3f803f5f3f0e,0xbf27be793e603f22,0xbf7cbf4ebee68000,0x3dfbbeacbf39bf75,
0x3dc93f0e3f623f80,0xbf75bf7bbf46bec4,0x3f223e48be95bf35,0x3ef13f553f7f3f6d,0xbf7fbf55bef10000,0x3e95be48bf22bf6d,0x3f463f7b3f753f35,0xbf62bf0ebdc93ec4,
0xbf7fbf55bef18000,0x3e95be48bf22bf6d,0x3f463f7b3f753f35,0xbf62bf0ebdc93ec4,0xbdc9bf0ebf62bf80,0x3f753f7b3f463ec4,0xbf22be483e953f35,0xbef1bf55bf7fbf6d,
0x3f513edbbd97bf0e,0x3dfb3f183f6a3f7f,0x3cc93f043f5f3f80,0xbf65bf80bf58bef1,0x3e603f2c3f733f7b,0xbf77bf78bf39be95,0xbf6fbf7dbf4abec4,0x3f423eacbe2fbf22,
0x3f133f673f7f3f55,0xbf7ebf4ebecf3dc9,0xbf80bf5cbefc8000,0x3ee6bd49bf09bf62,0xbf7abf3ebea13e48,0x3e89be79bf31bf75,0x3eb8be16bf1dbf6d,0x3f273f713f7c3f46,
0xbf2cbf75bf78bf35,0x3f7d3f463eacbe48,0xbedb3dc93f183f6d,0xbf04bf62bf80bf55,0xbd493ef13f5c3f80,0xbf4ebf7fbf67bf0e,0x3f713f223e16bec4,0xbe793e953f3e3f7b,
0x3f3e3e95be79bf35,0x3e163f223f713f7b,0xbf67bf7fbf4ebec4,0x3f5c3ef1bd49bf0e,0xbf80bf62bf048000,0x3f183dc9bedbbf55,0x3eac3f463f7d3f6d,0xbf78bf75bf2cbe48,
0xbf65bf043cc93f0e,0x3e60beacbf4abf7f,0xbe89bf3ebf7cbf6d,0x3f6a3f7d3f423e95,0x3f7f3f4e3eb8be48,0xbf13bd493efc3f62,0xbdfb3edb3f583f80,0xbf31bf78bf73bf22,
0xbee6bf5cbf80bf55,0x3f7a3f713f1d3dc9,0x3f773f2c3e2fbec4,0xbecf3e163f273f75,0x3d973f183f6f3f7b,0xbf51bf80bf5fbef1,0xbf7ebf67bf098000,0x3f393e79bea1bf46,
0xbe483ec43f553f80,0xbf0ebf6dbf7bbf35,0x3f7b3f6d3f0e0000,0xbf55bec43e483f35,0x3e48bec4bf55bf80,0x3f0e3f6d3f7b3f35,0xbf7bbf6dbf0e0000,0x3f553ec4be48bf35,
0xbf7bbf6dbf0e8000,0x3f553ec4be48bf35,0xbe483ec43f553f80,0xbf0ebf6dbf7bbf35,0x3f7b3f6d3f0e8000,0xbf55bec43e483f35,0x3e48bec4bf55bf80,0x3f0e3f6d3f7b3f35,
0x3f653f7d3f393e48,0xbf7abf2cbdfb3ef1,0xbe893eac3f513f80,0xbecfbf5cbf7fbf46,0xbf27bf78bf6fbf0e,0x3f7c3f673efcbdc9,0x3f1d3d49bf09bf6d,0x3cc93f183f733f75,
0xbee63e163f313f7b,0xbe60bf3ebf7ebf62,0xbf77bf71bf138000,0x3f6a3f04bd97bf22,0x3f423e79beb8bf55,0xbe2f3edb3f5f3f7f,0x3f4a3f803f583ec4,0xbf80bf4ebea13e95,
0x3f673ef1be16bf35,0xbf043dc93f2c3f7b,0xbd49bf22bf78bf6d,0x3f183f753f713f0e,0xbeac3e953f4e3f80,0xbe79bf46bf80bf55,0x3f3e3f7f3f5c3ec4,0xbf7dbf62bedb3e48,
0x3edb3f623f7d3f35,0xbf5cbf7fbf3ebe48,0x3f803f463e79bec4,0xbf4ebe953eac3f55,0xbf71bf75bf188000,0x3f783f223d49bf0e,0xbf2cbdc93f043f6d,0x3e16bef1bf67bf7b,
0x3f13bd49bf27bf7b,0xbdfb3f043f6f3f75,0x3f803f4e3e89bec4,0xbf65bedb3e603f46,0x3f093f713f733f0e,0xbf5fbf7dbf31bdc9,0xbecf3e793f4a3f80,0xbd97bf2cbf7cbf62,
0x3f513f803f423e48,0xbf7ebf5cbeb83e95,0xbcc93f183f773f6d,0xbee6bf67bf7abf22,0xbf58beac3ea13f55,0x3efcbe16bf39bf7f,0xbf6abf78bf1d8000,0x3f7f3f3e3e2fbef1,
0xbef13e483f463f80,0x3dc9bf0ebf75bf6d,0x3e953f553f7f3f35,0xbf22bf7bbf62bec4,0x3f623f7b3f220000,0xbf7fbf55be953ec4,0x3f753f0ebdc9bf35,0xbf46be483ef13f6d,
0xbf62bf7bbf228000,0x3f7f3f553e95bec4,0xbf75bf0e3dc93f35,0x3f463e48bef1bf6d,0xbef13e483f463f80,0x3dc9bf0ebf75bf6d,0x3e953f553f7f3f35,0xbf22bf7bbf62bec4,
0x3cc93f2c3f7e3f55,0xbea1bf5cbf7cbf22,0xbf093e163f423f80,0x3e89bedbbf6abf75,0x3f6f3f713efcbe48,0xbf7fbf4ebe603ef1,0x3f133f783f653ec4,0xbf4abf80bf39bdc9,
0xbf80bf3ebdfb3f0e,0x3f733f04be2fbf46,0xbf58bf7dbf278000,0x3f773f673ecfbe95,0xbeb83eac3f5f3f7b,0x3d97bf18bf7abf62,0xbf51be793ee63f6d,0x3f1dbd49bf31bf7f,
0x3e163f463f803f35,0xbeacbf62bf78bf0e,0x3f043f753f673ec4,0xbf2cbf7fbf4ebe48,0xbf183dc93f3e3f80,0x3edbbe95bf5cbf7b,0xbe793ef13f713f6d,0x3d49bf22bf7dbf55,
0xbf7dbf223d493f35,0x3f713ef1be79bf55,0xbf5cbe953edb3f6d,0x3f3e3dc9bf18bf7b,0xbf4ebf7fbf2c8000,0x3f673f753f04be48,0xbf78bf62beac3ec4,0x3f803f463e16bf0e,
0xbdfb3f183f7c3f55,0x3cc9bf2cbf7fbf46,0xbea13edb3f6f3f6d,0x3e60bf04bf77bf62,0xbefc3e793f583f7b,0x3ecfbeacbf65bf75,0xbf273d493f393f80,0x3f13be16bf4abf7f,
0xbf7ebf4ebe2f3f0e,0x3f803f3e3d97bf22,0xbf73bf67beb83ec4,0x3f7a3f5c3e89bef1,0xbf5fbf78bf093e48,0x3f6a3f713ee6be95,0xbf42bf80bf318000,0x3f513f7d3f1dbdc9,
0x3f003f003f003f00,0x3f003f003f003f00,0x3f003f003f003f00,0x3f003f003f003f00,0x3f003f003f003f00,0x3f003f003f003f00,0x3f003f003f003f00,0x3f003f003f003f00,
0xbf003f00bf003f00,0xbf003f00bf003f00,0xbf003f00bf003f00,0xbf003f00bf003f00,0xbf003f00bf003f00,0xbf003f00bf003f00,0xbf003f00bf003f00,0xbf003f00bf003f00,
0x3efc3f043f093f0e,0x3ecf3edb3ee63ef1,0x3f273f2c3f313f35,0x3f133f183f1d3f22,0x3dfb3e163e2f3e48,0x3cc93d493d973dc9,0x3ea13eac3eb83ec4,0x3e603e793e893e95,
0xbf5fbf5cbf58bf55,0xbf6abf67bf65bf62,0xbf42bf3ebf39bf35,0xbf51bf4ebf4abf46,0xbf7ebf7dbf7cbf7b,0xbf80bf80bf7fbf7f,0xbf73bf71bf6fbf6d,0xbf7abf78bf77bf75,
0xbf4ebf46bf3ebf35,0xbf67bf62bf5cbf55,0xbf78bf75bf71bf6d,0xbf80bf7fbf7dbf7b,0xbe16bdc9bd490000,0xbeacbe95be79be48,0xbf04bef1bedbbec4,0xbf2cbf22bf18bf0e,
0xbf18bf22bf2cbf35,0xbedbbef1bf04bf0e,0xbe79be95beacbec4,0xbd49bdc9be16be48,0xbf7dbf7fbf80bf80,0xbf71bf75bf78bf7b,0xbf5cbf62bf67bf6d,0xbf3ebf46bf4ebf55,
0xbeb8bedbbefcbf0e,0xbd97be16be60be95,0xbf51bf5cbf65bf6d,0xbf1dbf2cbf39bf46,0xbf80bf80bf7ebf7b,0xbf73bf78bf7cbf7f,0xbf58bf4ebf42bf35,0xbf77bf71bf6abf62,
0x3f6f3f673f5f3f55,0x3f7f3f7d3f7a3f75,0x3f133f043ee63ec4,0x3f4a3f3e3f313f22,0x3cc9bd49bdfbbe48,0x3ea13e793e2f3dc9,0xbf09bf18bf27bf35,0xbe89beacbecfbef1,
0xbf75bf7bbf7fbf80,0xbf46bf55bf62bf6d,0xbef1bf0ebf22bf35,0xbdc9be48be95bec4,0x3e953e483dc90000,0x3f223f0e3ef13ec4,0x3f623f553f463f35,0x3f7f3f7b3f753f6d,
0x3e953e483dc98000,0x3f223f0e3ef13ec4,0x3f623f553f463f35,0x3f7f3f7b3f753f6d,0x3f753f7b3f7f3f80,0x3f463f553f623f6d,0x3ef13f0e3f223f35,0x3dc93e483e953ec4,
0x3f093edb3ea13e48,0x3f5f3f4e3f393f22,0xbecfbf04bf1dbf35,0x3d97bd49be2fbe95,0x3f133f2c3f423f55,0x3dfb3e793eb83ef1,0x3f803f7d3f773f6d,0x3f653f713f7a3f7f,
0x3f583f673f733f7b,0x3efc3f183f313f46,0x3f6a3f5c3f4a3f35,0x3f7f3f803f7c3f75,0xbf51bf3ebf27bf0e,0xbf7ebf78bf6fbf62,0x3cc93e163e893ec4,0xbee6beacbe60bdc9,
0x3eac3ef13f183f35,0xbe79bdc93d493e48,0xbf3ebf22bf04bec4,0xbf7dbf75bf67bf55,0x3edb3e953e160000,0x3f5c3f463f2c3f0e,0x3f803f7f3f783f6d,0x3f4e3f623f713f7b,
0xbf71bf62bf4ebf35,0xbf78bf7fbf80bf7b,0xbf2cbf46bf5cbf6d,0xbe16be95bedbbf0e,0x3f673f753f7d3f80,0x3f043f223f3e3f55,0xbd493dc93e793ec4,0xbf18bef1beacbe48,
0xbf42bf5cbf6fbf7b,0xbe2fbeacbefcbf22,0xbf4abf2cbf09bec4,0xbf80bf7dbf73bf62,0x3ee63f183f393f55,0xbe60bd493dfb3e95,0x3f773f673f513f35,0x3f6a3f783f7f3f7f,
0x3f273f043eb83e48,0x3f7c3f713f5f3f46,0xbf1dbf3ebf58bf6d,0x3cc9be16bea1bef1,0xbf65bf4ebf31bf0e,0xbf7abf80bf7ebf75,0x3e893edb3f133f35,0xbecfbe79bd973dc9,
0x3f553f6d3f7b3f80,0x3e483ec43f0e3f35,0xbf0ebec4be480000,0xbf7bbf6dbf55bf35,0xbf55bf6dbf7bbf80,0xbe48bec4bf0ebf35,0x3f0e3ec43e480000,0x3f7b3f6d3f553f35,
0xbf0ebec4be488000,0xbf7bbf6dbf55bf35,0xbf55bf6dbf7bbf80,0xbe48bec4bf0ebf35,0x3f0e3ec43e488000,0x3f7b3f6d3f553f35,0x3f553f6d3f7b3f80,0x3e483ec43f0e3f35,
0xbf7fbf7dbf6fbf55,0xbf13bf3ebf5fbf75,0x3dfb3eac3f093f35,0xbf31bf04bea1bdc9,0x3f653f783f803f7b,0x3e603edb3f1d3f46,0x3e893d49be2fbec4,0x3f6a3f4e3f273ef1,
0x3d97be16beb8bf0e,0x3f513f2c3efc3e95,0xbf7ebf71bf58bf35,0xbf39bf5cbf73bf7f,0xbee6be79bcc93e48,0xbf7abf67bf4abf22,0x3f773f803f7c3f6d,0x3ecf3f183f423f62,
0x3f803f753f5c3f35,0x3f183f463f673f7b,0xbeacbdc93e163ec4,0xbf78bf62bf3ebf0e,0xbf2cbef1be790000,0xbf7dbf7fbf71bf55,0xbedbbf22bf4ebf6d,0x3f043e953d49be48,
0x3d493e953f043f35,0xbf4ebf22bedbbe48,0xbf71bf7fbf7dbf6d,0xbe79bef1bf2cbf55,0xbf3ebf62bf78bf80,0x3e16bdc9beacbf0e,0x3f673f463f183ec4,0x3f5c3f753f803f7b,
0xbf7abf80bf73bf55,0xbe89bf04bf39bf62,0x3eb83f183f4a3f6d,0xbf27bedbbe2f3dc9,0x3f133eac3d97be48,0x3f7e3f7d3f6a3f46,0xbf80bf78bf5fbf35,0xbee6bf2cbf58bf75,
0x3e60bd49bea1bf0e,0x3f773f5c3f313ef1,0xbf6fbf4ebf1dbec4,0xbf42bf67bf7cbf7f,0x3f513f713f7f3f7b,0xbdfb3e163ecf3f22,0x3cc9be79befcbf35,0x3f653f3e3f093e95,
0xbf22bf55bf75bf80,0x3ef13e48bdc9bec4,0x3f7f3f7b3f623f35,0x3e953f0e3f463f6d,0xbf46bf0ebe950000,0xbf62bf7bbf7fbf6d,0x3dc9be48bef1bf35,0x3f753f553f223ec4,
0x3f463f0e3e958000,0x3f623f7b3f7f3f6d,0xbdc93e483ef13f35,0xbf75bf55bf22bec4,0xbf22bf55bf75bf80,0x3ef13e48bdc9bec4,0x3f7f3f7b3f623f35,0x3e953f0e3f463f6d,
0x3ecf3f2c3f5f3f7b,0xbf42bf04be603dc9,0x3e2fbe16bee6bf35,0x3f7e3f673f393ef1,0x3f803f713f4a3f0e,0x3ea13f183f513f75,0xbf58bf78bf7fbf6d,0x3e89bd49beb8bf22,
0xbf6abf3ebefcbe48,0xbf27bf5cbf7abf7f,0x3f7c3f7d3f653f35,0x3dfb3edb3f313f62,0x3cc93eac3f1d3f55,0xbf73bf4ebf13be95,0x3f093e79bd97bec4,0x3f773f803f6f3f46,
0x3e79bdc9bedbbf35,0x3f803f753f4e3f0e,0x3e163ef13f3e3f6d,0xbf71bf46bf04be48,0x3f5c3f223eac0000,0x3f2c3f623f7d3f7b,0xbf18be953d493ec4,0xbf67bf7fbf78bf55,
0x3f783f7f3f673f35,0xbd493e953f183f55,0xbf7dbf62bf2cbec4,0xbeacbf22bf5cbf7b,0x3f043f463f713f80,0xbf3ebef1be163e48,0xbf4ebf75bf80bf6d,0x3edb3dc9be79bf0e,
0xbf77bf4ebf09be48,0xbeb8bf2cbf65bf7f,0x3f7f3f673f313ec4,0x3e2f3f043f4a3f75,0xbf7ebf78bf51bf0e,0x3cc9beacbf27bf62,0x3f733f803f6a3f35,0xbe603e163efc3f46,
0xbe89bf18bf58bf7b,0x3f6f3f3e3ee63dc9,0x3d973edb3f393f6d,0xbf7cbf5cbf1dbe95,0x3dfbbe79bf13bf55,0x3f803f713f423ef1,0xbea13d493ecf3f35,0xbf7abf7dbf5fbf22,
0x3ec43f353f6d3f80,0xbf6dbf35bec40000,0xbec4bf35bf6dbf80,0x3f6d3f353ec40000,0x3ec43f353f6d3f80,0xbf6dbf35bec40000,0xbec4bf35bf6dbf80,0x3f6d3f353ec40000,
0xbf6dbf35bec48000,0xbec4bf35bf6dbf80,0x3f6d3f353ec48000,0x3ec43f353f6d3f80,0xbf6dbf35bec48000,0xbec4bf35bf6dbf80,0x3f6d3f353ec48000,0x3ec43f353f6d3f80,
0x3f1d3e79be2fbf0e,0x3f393f713f7f3f62,0xbee6bd493eb83f35,0xbf58bf7dbf77bf46,0x3f5f3f183e60be48,0x3ecf3f3e3f733f7f,0xbf42bedbbcc93ec4,0xbf13bf5cbf7ebf75,
0x3f4a3f783f7c3f55,0xbf31beac3d973ef1,0xbf65bf80bf6fbf35,0x3f093e16be89bf22,0x3efc3f4e3f7a3f7b,0xbf6abf2cbea13dc9,0xbf27bf67bf80bf6d,0x3f513f043dfbbe95,
0xbf5cbf7fbf71bf35,0x3f2c3e95be16bf0e,0x3f183f623f803f6d,0xbf67bf22be793e48,0xbf78bf46bedb0000,0xbd49bef1bf4ebf7b,0x3f7d3f753f3e3ec4,0xbeac3dc93f043f55,
0x3f043dc9beacbf35,0x3f3e3f753f7d3f55,0xbf4ebef1bd493ec4,0xbedbbf46bf78bf7b,0xbe79bf22bf67bf80,0x3f803f623f183e48,0xbe163e953f2c3f6d,0xbf71bf7fbf5cbf0e,
0xbf39beac3dfb3f0e,0xbee6bf4ebf7cbf75,0x3e60be79bf27bf6d,0x3f5f3f803f6a3f22,0x3eb83f3e3f773f7b,0xbf7fbf5cbf09bdc9,0xbf51bf7dbf73bf35,0x3f4a3edbbcc9bef1,
0xbf31bf71bf7ebf55,0x3f653f183e2fbe95,0x3f7a3f783f423ec4,0xbefcbd493ecf3f46,0xbf6fbf2cbe893e48,0xbd97bf04bf58bf7f,0x3f133e16bea1bf35,0x3f1d3f673f803f62,
0xbdc9bf0ebf62bf80,0x3f753f7b3f463ec4,0xbf22be483e953f35,0xbef1bf55bf7fbf6d,0x3f7f3f553ef10000,0xbe953e483f223f6d,0xbf46bf7bbf75bf35,0x3f623f0e3dc9bec4,
0x3f7f3f553ef18000,0xbe953e483f223f6d,0xbf46bf7bbf75bf35,0x3f623f0e3dc9bec4,0x3dc93f0e3f623f80,0xbf75bf7bbf46bec4,0x3f223e48be95bf35,0x3ef13f553f7f3f6d,
0xbf7cbf71bf27be48,0x3f1d3e16beb8bf46,0x3f313e79be89bf35,0x3ea13f3e3f7a3f75,0x3f093d49bee6bf55,0x3efc3f5c3f803f62,0x3ecf3f4e3f7e3f6d,0xbf7fbf67bf13bdc9,
0x3e2fbeacbf42bf7b,0x3f4a3f7d3f6f3f22,0x3f393f783f773f35,0xbf73bf2cbe603e95,0x3f583f803f653f0e,0xbf5fbf04bcc93ef1,0xbf6abf18bdfb3ec4,0x3d97bedbbf51bf7f,
0xbf3ebe953e793f35,0xbe16bf22bf71bf7b,0x3f673f7f3f4e3ec4,0xbf5cbef13d493f0e,0x3f803f623f040000,0xbf18bdc93edb3f55,0xbeacbf46bf7dbf6d,0x3f783f753f2c3e48,
0xbf2cbf75bf78bf35,0x3f7d3f463eacbe48,0xbedb3dc93f183f6d,0xbf04bf62bf80bf55,0xbd493ef13f5c3f80,0xbf4ebf7fbf67bf0e,0x3f713f223e16bec4,0xbe793e953f3e3f7b,
0xbea13e793f393f7b,0xbf09bf67bf7ebf46,0xbf5fbf80bf51bec4,0x3f6f3f183d97bef1,0x3f273e16becfbf55,0x3e2f3f2c3f773f75,0x3f1d3f713f7a3f35,0xbf80bf5cbee63dc9,
0xbf73bf78bf31be48,0x3f583edbbdfbbf22,0x3efcbd49bf13bf6d,0x3eb83f4e3f7f3f62,0x3f423f7d3f6a3f0e,0xbf7cbf3ebe893e95,0xbf4abeac3e603f35,0x3cc9bf04bf65bf7f,
0xbe483ec43f553f80,0xbf0ebf6dbf7bbf35,0x3f7b3f6d3f0e0000,0xbf55bec43e483f35,0x3e48bec4bf55bf80,0x3f0e3f6d3f7b3f35,0xbf7bbf6dbf0e0000,0x3f553ec4be48bf35,
0xbf7bbf6dbf0e8000,0x3f553ec4be48bf35,0xbe483ec43f553f80,0xbf0ebf6dbf7bbf35,0x3f7b3f6d3f0e8000,0xbf55bec43e483f35,0x3e48bec4bf55bf80,0x3f0e3f6d3f7b3f35,
0x3ea13f4e3f803f55,0xbf58bf80bf4abe95,0xbf5fbedb3e2f3f35,0x3eb8be79bf42bf7f,0x3d97bf04bf6abf7b,0x3f133f713f773f22,0x3f7e3f3e3e60bec4,0xbf31be163ee63f62,
0xbf73bf18bcc93f0e,0x3f09bd49bf1dbf75,0xbefcbf67bf7cbf35,0x3f6f3f783f273dc9,0x3f7f3f5c3ecfbe48,0xbf51beac3e893f46,0x3dfb3f2c3f7a3f6d,0xbf39bf7dbf65bef1,
0x3edb3f623f7d3f35,0xbf5cbf7fbf3ebe48,0x3f803f463e79bec4,0xbf4ebe953eac3f55,0xbf71bf75bf180000,0x3f783f223d49bf0e,0xbf2cbdc93f043f6d,0x3e16bef1bf67bf7b,
0xbf67bef13e163f35,0x3f04bdc9bf2cbf7b,0x3d493f223f783f6d,0xbf18bf75bf71bf0e,0x3eacbe95bf4ebf80,0x3e793f463f803f55,0xbf3ebf7fbf5cbec4,0x3f7d3f623edbbe48,
0x3e2f3f3e3f7f3f55,0xbf1dbf78bf6abef1,0xbf39be163efc3f6d,0x3ea1beacbf58bf7f,0xbf7abf67bee63e48,0x3f773f18bcc9bf22,0xbeb8bf5cbf7ebf35,0x3f423f803f513e95,
0xbf7cbf2cbd973f0e,0x3f4a3e79becfbf62,0xbf31bf7dbf5fbec4,0x3f733f713f09bdc9,0x3e60bedbbf65bf7b,0x3e893f4e3f803f46,0x3f6f3f04bdfbbf35,0xbf27bd493f133f75,
0x3ef1be48bf46bf80,0xbdc93f0e3f753f6d,0xbe95bf55bf7fbf35,0x3f223f7b3f623ec4,0xbf62bf7bbf220000,0x3f7f3f553e95bec4,0xbf75bf0e3dc93f35,0x3f463e48bef1bf6d,
0x3f623f7b3f228000,0xbf7fbf55be953ec4,0x3f753f0ebdc9bf35,0xbf46be483ef13f6d,0x3ef1be48bf46bf80,0xbdc93f0e3f753f6d,0xbe95bf55bf7fbf35,0x3f223f7b3f623ec4,
0x3f313d49bf1dbf7b,0xbee63e793f513f7f,0x3f7a3f18bd97bf35,0xbf5fbeac3eb83f62,0xbecfbf67bf77bf0e,0x3f273f7d3f583e95,0x3e2fbf04bf73bf6d,0x3dfb3f3e3f803f46,
0x3f393f803f4a3e48,0xbf65bf78bf133dc9,0x3e603f4e3f7f3f35,0xbefcbf71bf6fbef1,0x3f6a3edbbe89bf55,0xbf42be163f093f75,0x3f7c3f5c3ea1bec4,0xbf7ebf2cbcc93f22,
0x3f7d3f22bd49bf35,0xbf71bef13e793f55,0x3f5c3e95bedbbf6d,0xbf3ebdc93f183f7b,0x3f4e3f7f3f2c0000,0xbf67bf75bf043e48,0x3f783f623eacbec4,0xbf80bf46be163f0e,
0x3e163f463f803f35,0xbeacbf62bf78bf0e,0x3f043f753f673ec4,0xbf2cbf7fbf4ebe48,0xbf183dc93f3e3f80,0x3edbbe95bf5cbf7b,0xbe793ef13f713f6d,0x3d49bf22bf7dbf55,
0x3f1d3f7d3f513e48,0xbf31bf80bf42bdc9,0x3ee63f713f6a3ec4,0xbf09bf78bf5fbe95,0x3e893f5c3f7a3f0e,0xbeb8bf67bf73bef1,0x3d973f3e3f803f35,0xbe2fbf4ebf7ebf22,
0xbf4abe163f133f7b,0x3f393d49bf27bf7f,0xbf65beac3ecf3f6d,0x3f583e79befcbf75,0xbf77bf043e603f55,0x3f6f3edbbea1bf62,0xbf7fbf2c3cc93f35,0x3f7c3f18bdfbbf46,
0xbf8000003f80,0xbf8000003f80,0xbf8000003f80,0xbf8000003f80,0xbf8000003f80,0xbf8000003f80,0xbf8000003f80,0xbf8000003f80,
0x3f808000bf808000,0x3f808000bf808000,0x3f808000bf808000,0x3f808000bf808000,0x3f808000bf808000,0x3f808000bf808000,0x3f808000bf808000,0x3f808000bf808000,
0x3e89bf78be603f7b,0x3eb8bf71bea13f75,0x3d97bf80bcc93f80,0x3e2fbf7dbdfb3f7f,0x3f1dbf4ebf133f55,0x3f31bf3ebf273f46,0x3ee6bf67becf3f6d,0x3f09bf5cbefc3f62,
0x3f773e79bf7abe48,0x3f6f3eacbf73be95,0x3f7f3d49bf808000,0x3f7c3e16bf7ebdc9,0x3f4a3f18bf51bf0e,0x3f393f2cbf42bf22,0x3f653edbbf6abec4,0x3f583f04bf5fbef1,
0x3f4ebf22bf3e3f35,0x3f67bef1bf5c3f0e,0x3f78be95bf713ec4,0x3f80bdc9bf7d3e48,0x3e16bf7fbd493f80,0x3eacbf75be793f7b,0x3f04bf62bedb3f6d,0x3f2cbf46bf183f55,
0x3f183f46bf2cbf35,0x3edb3f62bf04bf55,0x3e793f75beacbf6d,0x3d493f7fbe16bf7b,0x3f7d3dc9bf808000,0x3f713e95bf78be48,0x3f5c3ef1bf67bec4,0x3f3e3f22bf4ebf0e,
0x3f6a3eacbf77be48,0x3f423f18bf58bef1,0x3f7cbe79bf733ec4,0x3f7e3d49bf803dc9,0x3f39bf3ebf1d3f55,0x3f65bf04bf513f22,0x3e60bf7dbd973f80,0x3efcbf67beb83f75,
0xbecf3f713e89bf7b,0xbf273f4e3f09bf62,0x3e2f3f78bea1bf6d,0xbdfb3f80bcc9bf7f,0x3f313f2cbf4abf0e,0x3ee63f5cbf13bf46,0x3f7a3e16bf7f8000,0x3f5f3edbbf6fbe95,
0x3e95bf7bbdc93f80,0x3f22bf55bef13f6d,0x3f62bf0ebf463f35,0x3f7fbe48bf753ec4,0x3f753e48bf7f0000,0x3f463f0ebf62bec4,0x3ef13f55bf22bf35,0x3dc93f7bbe95bf6d,
0x3f753e48bf7f8000,0x3f463f0ebf62bec4,0x3ef13f55bf22bf35,0x3dc93f7bbe95bf6d,0xbe953f7b3dc9bf80,0xbf223f553ef1bf6d,0xbf623f0e3f46bf35,0xbf7f3e483f75bec4,
0x3f7abeacbf653f0e,0x3f773e16bf803dc9,0x3eb8bf78bdfb3f80,0x3f42bf3ebf133f62,0xbe2f3f80bd97bf7b,0xbf1d3f5c3ecfbf75,0x3f393f18bf5fbec4,0x3ea13f67bf09bf46,
0x3e603f71bee6bf55,0xbe893f7d3cc9bf7f,0x3f6f3e79bf7e8000,0x3f273f2cbf51bef1,0xbf7cbd493f7fbe48,0xbf4abf043f6a3e95,0xbf313f4e3efcbf6d,0xbf733edb3f58bf22,
0x3eac3f62bf18bf35,0xbe793f7fbd49bf7b,0xbf3e3f463f04bf6d,0xbf7d3e953f67bf0e,0x3edbbf75be163f80,0x3f5cbf22bf2c3f55,0x3f80bdc9bf783ec4,0x3f4e3ef1bf71be48,
0xbf713ef13f4ebf35,0xbf78bdc93f80be48,0xbf2cbf223f5c3ec4,0xbe16bf753edb3f55,0x3f673e95bf7d8000,0x3f043f46bf3ebf0e,0xbd493f7fbe79bf6d,0xbf183f623eacbf7b,
0xbf7f3e793f6abf0e,0xbf51bedb3f773dc9,0xbdfb3f80be60bf6d,0xbf393f4e3ee6bf75,0x3f733e16bf803e48,0x3f093f3ebf4abef1,0x3efcbf71be2f3f80,0x3f6fbf04bf423f46,
0xbd97bf783ecf3f55,0x3f13bf67be893f7f,0xbf7e3d493f7abec4,0xbf31bf183f653e95,0xbea13f7dbcc9bf7b,0xbf583f2c3f1dbf62,0x3f5f3eacbf7c8000,0x3eb83f5cbf27bf22,
0x3f0ebf6dbe483f80,0x3f7bbec4bf553f35,0x3f553ec4bf7b0000,0x3e483f6dbf0ebf35,0xbf0e3f6d3e48bf80,0xbf7b3ec43f55bf35,0xbf55bec43f7b0000,0xbe48bf6d3f0e3f35,
0x3f553ec4bf7b8000,0x3e483f6dbf0ebf35,0xbf0e3f6d3e48bf80,0xbf7b3ec43f55bf35,0xbf55bec43f7b8000,0xbe48bf6d3f0e3f35,0x3f0ebf6dbe483f80,0x3f7bbec4bf553f35,
0x3f273f18bf6abe48,0xbe2f3f80be89bf62,0x3f1dbf67be603f80,0x3f80be79bf653f22,0xbea1bf5c3f313f0e,0x3f09bf71bdfb3f7f,0xbf5f3f2c3f13bf6d,0xbf6fbe163f7fbe95,
0xbf423f4e3ecfbf7b,0xbf7c3d493f77bef1,0x3f4a3edbbf7a8000,0x3cc93f78bee6bf46,0x3f73bf04bf393f55,0x3f583eacbf7e3dc9,0xbefcbf3e3f513ec4,0x3eb8bf7d3d973f75,
0xbf803e953f5cbf35,0xbf18bf223f673e48,0x3eacbf7f3e163f6d,0x3f78bef1bf3e3f55,0x3f2cbf62be793f80,0x3f7dbdc9bf713f0e,0x3edb3f46bf4ebec4,0xbf043f753d49bf7b,
0xbd49bf753f043f35,0x3f4ebf46bedb3f7b,0x3f713dc9bf7d3ec4,0x3e793f62bf2cbf0e,0x3f3e3ef1bf788000,0xbe163f7fbeacbf55,0xbf673f223f18bf6d,0xbf5cbe953f80be48,
0x3f58bf3ebee63f7b,0x3f5f3e79bf803e95,0xbf6abe163f7ebec4,0xbd97bf713f133f22,0x3e2f3f67bf27bf0e,0xbf4a3f4e3eb8bf7f,0x3f39bf5cbe893f80,0x3f733d49bf7a3ef1,
0x3f093f2cbf65be48,0xbefc3f78bcc9bf75,0x3ecfbf7d3dfb3f6d,0x3f7fbeacbf513f46,0xbf7c3edb3f42bf55,0xbf1dbf183f6f3dc9,0x3f313f04bf778000,0xbea13f80be60bf62,
0x3f46bf55be953f80,0x3f623e48bf7f3ec4,0xbdc93f7bbef1bf35,0xbf753f0e3f22bf6d,0xbf22bf0e3f750000,0x3ef1bf7b3dc93f6d,0x3f7fbe48bf623f35,0x3e953f55bf46bec4,
0x3f223f0ebf758000,0xbef13f7bbdc9bf6d,0xbf7f3e483f62bf35,0xbe95bf553f463ec4,0x3f46bf55be953f80,0x3f623e48bf7f3ec4,0xbdc93f7bbef1bf35,0xbf753f0e3f22bf6d,
0xbeb83f80be89bf55,0xbf7f3e793f58bf46,0x3f51bf4ebea13f80,0x3f4a3eacbf803e95,0x3f393edbbf7e3e48,0xbee63f7dbe2fbf62,0xbe60bf5c3f423ec4,0x3f5fbf3ebecf3f7f,
0xbf6fbd493f77bf0e,0x3d97bf783f093f22,0x3f133f18bf738000,0xbf1d3f713cc9bf75,0xbf313f673dfbbf7b,0xbf65be163f7cbef1,0x3f7abf04bf273f6d,0x3efc3f2cbf6abdc9,
0x3e79bf7f3edb3f35,0x3f80be95bf4e3f55,0x3e163f62bf3ebec4,0xbf713f223f04bf7b,0x3f5cbf46beac3f80,0x3f2c3ef1bf7d3e48,0xbf183f75bd49bf6d,0xbf67bdc93f78bf0e,
0x3f78bdc9bf673f35,0xbd493f75bf18bf0e,0xbf7d3ef13f2cbf6d,0xbeacbf463f5c3e48,0x3f043f22bf718000,0xbf3e3f623e16bf7b,0xbf4ebe953f80bec4,0x3edbbf7f3e793f55,
0xbefc3f7dbe60bf55,0xbf6abd493f73bf22,0x3f27bf713cc93f6d,0x3f513e79bf7e3ef1,0xbf4a3f5c3e2fbf7b,0xbf31bedb3f7fbe95,0x3f65bf3ebeb83f80,0x3f093f18bf773dc9,
0xbf5fbe163f7abf0e,0x3ecfbf803ea13f46,0x3f423eacbf803ec4,0xbf133f78bdfbbf62,0xbf1dbf043f7cbe48,0x3f39bf67bd973f75,0x3ee63f2cbf6f8000,0xbf583f4e3e89bf7f,
0x3f6dbf35bec43f80,0x3ec43f35bf6d0000,0xbf6d3f353ec4bf80,0xbec4bf353f6d0000,0x3f6dbf35bec43f80,0x3ec43f35bf6d0000,0xbf6d3f353ec4bf80,0xbec4bf353f6d0000,
0x3ec43f35bf6d8000,0xbf6d3f353ec4bf80,0xbec4bf353f6d8000,0x3f6dbf35bec43f80,0x3ec43f35bf6d8000,0xbf6d3f353ec4bf80,0xbec4bf353f6d8000,0x3f6dbf35bec43f80,
0xbf7e3f043f13bf7b,0xbcc9bf673f423e95,0x3f73bf2cbecf3f80,0x3e603f4ebf5fbdc9,0xbf773e163f58bf55,0x3eb8bf803ee63f22,0x3f7fbeacbf393f6d,0xbe2f3f78bf1dbef1,
0xbdfbbf5c3f513e48,0x3f80bedbbf273f75,0x3ea13f3ebf6a8000,0xbf7a3f183efcbf7f,0x3e89bf7d3f093f0e,0x3f6fbd49bf653f46,0xbd973f71bf31bec4,0xbf7c3e793f4abf62,
0x3f5c3dc9bf713f35,0xbf2c3f75be16bf55,0xbf18bef13f80bec4,0x3f67bf46be793f7b,0x3f78bf22bedb3f80,0x3d493f62bf4ebe48,0xbf7d3e953f3ebf6d,0x3eacbf7f3f043f0e,
0xbf043f7fbeacbf35,0xbf3ebe953f7dbf0e,0x3f4ebf62bd493f6d,0x3edb3f22bf783e48,0x3e793f46bf678000,0xbf803ef13f18bf7b,0x3e16bf753f2c3ec4,0x3f71bdc9bf5c3f55,
0x3cc9bf673f4a3e48,0x3f73be16bf513f62,0x3f093f04bf7f3ec4,0xbf773f2c3eb8bf7f,0xbf6a3d493f5fbf55,0x3f27bf783e603f46,0x3f7cbf18bee63f80,0xbdfb3f71bf39be95,
0x3f80bedbbf1d3f7b,0xbea13f7dbf13bef1,0xbf583f5c3d97bf6d,0xbe89bf3e3f6fbdc9,0x3ecfbf803efc3f0e,0x3f423e79bf7a3f22,0x3e2f3f4ebf658000,0xbf7e3eac3f31bf75,
0x3f7fbf0ebef13f80,0xbe953f7bbf22bec4,0xbf46be483f75bf35,0x3f62bf55bdc93f6d,0x3dc93f55bf620000,0xbf753e483f46bf6d,0x3f22bf7b3e953f35,0x3ef13f0ebf7f3ec4,
0x3dc93f55bf628000,0xbf753e483f46bf6d,0x3f22bf7b3e953f35,0x3ef13f0ebf7f3ec4,0xbf7f3f0e3ef1bf80,0x3e95bf7b3f223ec4,0x3f463e48bf753f35,0xbf623f553dc9bf6d,
0xbf13bedb3f7fbf0e,0x3f7ebf18becf3f7f,0x3f80bf04befc3f80,0xbee63f80bf09bef1,0x3f7abf2cbea13f7b,0xbe893f78bf31be95,0xbeb83f7dbf1dbec4,0xbf27beac3f7cbf22,
0x3f51bf673d973f55,0x3dfb3f4ebf6a3dc9,0x3cc93f5cbf5f8000,0xbf653d493f58bf62,0x3e603f3ebf733e48,0xbf773e793f39bf75,0xbf6f3e163f4abf6d,0x3f42bf713e2f3f46,
0xbf3e3f75be79bf35,0xbe16bf463f71be48,0x3f67bdc9bf4e3f6d,0xbf5c3f62bd49bf55,0x3f80bef1bf043f80,0xbf183f7fbedbbf0e,0xbeacbf223f7dbec4,0x3f78be95bf2c3f7b,
0xbf2cbe953f78bf35,0x3f7dbf22beac3f7b,0xbedb3f7fbf18bec4,0xbf04bef13f80bf0e,0xbd493f62bf5c8000,0xbf4ebdc93f67bf55,0x3f71bf46be163f6d,0xbe793f75bf3ebe48,
0x3ee63f04bf803f0e,0xbf7a3eac3f1dbf7f,0xbf773f3e3e2fbf6d,0x3ecfbf7d3f273e95,0xbd97bf4e3f6fbe48,0x3f513d49bf5f3f62,0x3f7ebedbbf093f80,0xbf393f78bea1bf22,
0xbf653f5cbcc9bf55,0x3e60bf713f4a3dc9,0xbe89bf2c3f7cbec4,0x3f6abe16bf423f75,0x3f7fbf18beb83f7b,0xbf133f80befcbef1,0xbdfb3f67bf588000,0xbf31be793f73bf46,
0x3f7bbec4bf0e3f80,0xbf553f6dbe48bf35,0x3e48bf6d3f550000,0x3f0e3ec4bf7b3f35,0xbf7b3ec43f0ebf80,0x3f55bf6d3e483f35,0xbe483f6dbf550000,0xbf0ebec43f7bbf35,
0xbe483f6dbf558000,0xbf0ebec43f7bbf35,0x3f7bbec4bf0e3f80,0xbf553f6dbe48bf35,0x3e48bf6d3f558000,0x3f0e3ec4bf7b3f35,0xbf7b3ec43f0ebf80,0x3f55bf6d3e483f35,
0x3ee6bf7d3f313e48,0x3e603f2cbf7e3ef1,0x3f77beacbf133f80,0xbf6a3f5cbd97bf46,0xbf423f78beb8bf0e,0x3e2fbf673f5fbdc9,0xbf4abd493f58bf6d,0x3f80bf18bea13f75,
0x3f65be16bf393f7b,0xbf7a3f3e3dfbbf62,0xbe893f71bf518000,0xbecfbf043f7fbf22,0xbf27be793f6fbf55,0x3f7cbedbbefc3f7f,0x3f1dbf803f093ec4,0x3cc93f4ebf733e95,
0xbedbbef13f7dbf35,0x3f5cbdc9bf3e3f7b,0xbf803f223e79bf6d,0x3f4ebf753eac3f0e,0x3f71be95bf183f80,0xbf783f463d49bf55,0x3f2cbf7f3f043ec4,0xbe163f62bf673e48,
0x3f67bf623e163f35,0xbf043f7fbf2cbe48,0xbd49bf463f78bec4,0x3f183e95bf713f55,0xbeac3f75bf4e8000,0xbe79bf223f80bf0e,0x3f3e3dc9bf5c3f6d,0xbf7d3ef13edbbf7b,
0xbf513d493f42bf7b,0x3f7ebf04beb83f75,0x3cc9bf4e3f77bec4,0x3ee63edbbf7a3f46,0x3f58bf713ea13f0e,0xbefc3f7dbf39bdc9,0x3f6abe79bf1d3f80,0xbf7f3f2c3e2fbf62,
0x3f13bf803f273e48,0xbdfb3f5cbf6f3e95,0x3f80bf18be893f6d,0xbf653f67be60bf22,0x3f093eacbf733f55,0xbf5f3e163f31bf7f,0xbecf3f78bf4a8000,0xbd97bf3e3f7cbef1,
0x3f62be48bf223f80,0xbf7f3f0e3e95bf6d,0x3f75bf553dc93f35,0xbf463f7bbef1bec4,0x3ef1bf7b3f460000,0xbdc93f55bf753ec4,0xbe95bf0e3f7fbf35,0x3f223e48bf623f6d,
0xbef13f7bbf468000,0x3dc9bf553f75bec4,0x3e953f0ebf7f3f35,0xbf22be483f62bf6d,0x3f62be48bf223f80,0xbf7f3f0e3e95bf6d,0x3f75bf553dc93f35,0xbf463f7bbef1bec4,
0x3f80bf2cbdfb3f55,0xbf733f5cbe2fbf22,0x3f58be16bf273f80,0xbf773edb3ecfbf75,0x3eb8bf713f5fbe48,0xbd973f4ebf7a3ef1,0x3f51bf783ee63ec4,0xbf1d3f80bf31bdc9,
0x3cc93f3ebf7e3f0e,0xbea1bf043f7cbf46,0xbf093f7dbf428000,0x3e89bf673f6abe95,0x3f6fbeacbefc3f7b,0xbf7f3f183e60bf62,0x3f133e79bf653f6d,0xbf4a3d493f39bf7f,
0x3f7dbf463d493f35,0xbf713f62be79bf0e,0x3f5cbf753edb3ec4,0xbf3e3f7fbf18be48,0x3f4ebdc9bf2c3f80,0xbf673e953f04bf7b,0x3f78bef1beac3f6d,0xbf803f223e16bf55,
0x3e163f22bf803f35,0xbeacbef13f78bf55,0x3f043e95bf673f6d,0xbf2cbdc93f4ebf7b,0xbf183f7fbf3e8000,0x3edbbf753f5cbe48,0xbe793f62bf713ec4,0x3d49bf463f7dbf0e,
0x3f7ebf18be2f3f55,0xbf803f2c3d97bf46,0x3f73bedbbeb83f6d,0xbf7a3f043e89bf62,0x3f5fbe79bf093f7b,0xbf6a3eac3ee6bf75,0x3f42bd49bf313f80,0xbf513e163f1dbf7f,
0xbdfb3f4ebf7c3f0e,0x3cc9bf3e3f7fbf22,0xbea13f67bf6f3ec4,0x3e60bf5c3f77bef1,0xbefc3f78bf583e48,0x3ecfbf713f65be95,0xbf273f80bf398000,0x3f13bf7d3f4abdc9,
0xbf8000003f80,0xbf8000003f80,0xbf8000003f80,0xbf8000003f80,0xbf8000003f80,0xbf8000003f80,0xbf8000003f80,0xbf8000003f80,
0x3f808000bf808000,0x3f808000bf808000,0x3f808000bf808000,0x3f808000bf808000,0x3f808000bf808000,0x3f808000bf808000,0x3f808000bf808000,0x3f808000bf808000,
0x3f5fbf04bf583f0e,0x3f6abedbbf653ef1,0x3f42bf2cbf393f35,0x3f51bf18bf4a3f22,0x3f7ebe16bf7c3e48,0x3f80bd49bf7f3dc9,0x3f73beacbf6f3ec4,0x3f7abe79bf773e95,
0x3efc3f5cbf09bf55,0x3ecf3f67bee6bf62,0x3f273f3ebf31bf35,0x3f133f4ebf1dbf46,0x3dfb3f7dbe2fbf7b,0x3cc93f80bd97bf7f,0x3ea13f71beb8bf6d,0x3e603f78be89bf75,
0x3f183f46bf2cbf35,0x3edb3f62bf04bf55,0x3e793f75beacbf6d,0x3d493f7fbe16bf7b,0x3f7d3dc9bf800000,0x3f713e95bf78be48,0x3f5c3ef1bf67bec4,0x3f3e3f22bf4ebf0e,
0xbf4e3f223f3ebf35,0xbf673ef13f5cbf0e,0xbf783e953f71bec4,0xbf803dc93f7dbe48,0xbe163f7f3d49bf80,0xbeac3f753e79bf7b,0xbf043f623edbbf6d,0xbf2c3f463f18bf55,
0xbf6f3edb3f5fbf0e,0xbf7f3e163f7abe95,0xbf133f5c3ee6bf6d,0xbf4a3f2c3f31bf46,0xbcc93f80bdfbbf7b,0xbea13f783e2fbf7f,0x3f093f4ebf27bf35,0x3e893f71becfbf62,
0xbeb8bf673efc3f55,0xbd97bf7d3e603f75,0xbf51bf043f653ec4,0xbf1dbf3e3f393f22,0xbf803d493f7ebe48,0xbf73be793f7c3dc9,0xbf583f183f42bf35,0xbf773eac3f6abef1,
0xbe953f7b3dc9bf80,0xbf223f553ef1bf6d,0xbf623f0e3f46bf35,0xbf7f3e483f75bec4,0xbf75be483f7f0000,0xbf46bf0e3f623ec4,0xbef1bf553f223f35,0xbdc9bf7b3e953f6d,
0xbf75be483f7f8000,0xbf46bf0e3f623ec4,0xbef1bf553f223f35,0xbdc9bf7b3e953f6d,0x3e95bf7bbdc93f80,0x3f22bf55bef13f6d,0x3f62bf0ebf463f35,0x3f7fbe48bf753ec4,
0xbf58bedb3f733e48,0xbefcbf4e3f313f22,0xbf6a3f043f4abf35,0xbf7f3d493f7cbe95,0x3f51bf2cbf273f55,0x3f7ebe79bf6f3ef1,0xbcc9bf7d3e893f6d,0x3ee6bf71be603f7f,
0x3f09bf67bea13f7b,0x3f5fbf18bf393f46,0xbecfbf5c3f1d3f35,0x3d97bf803e2f3f75,0x3f133f3ebf42bf0e,0x3dfb3f78beb8bf62,0x3f80be16bf773ec4,0x3f653eacbf7abdc9,
0x3f71bef1bf4e3f35,0x3f783dc9bf803e48,0x3f2c3f22bf5cbec4,0x3e163f75bedbbf55,0xbf67be953f7d0000,0xbf04bf463f3e3f0e,0x3d49bf7f3e793f6d,0x3f18bf62beac3f7b,
0x3eac3f62bf18bf35,0xbe793f7fbd49bf7b,0xbf3e3f463f04bf6d,0xbf7d3e953f67bf0e,0x3edbbf75be163f80,0x3f5cbf22bf2c3f55,0x3f80bdc9bf783ec4,0x3f4e3ef1bf71be48,
0xbf273f5c3eb8bf7b,0xbf7c3eac3f5fbf22,0x3f1d3f2cbf58bec4,0xbcc93f7dbea1bf62,0x3f65bf18bf313f55,0x3f7a3d49bf7e3e95,0xbe89bf673f133f35,0x3ecfbf78bd973f7f,
0xbf42bf043f6f3e48,0xbe2fbf713efc3f46,0xbf4a3f3e3f09bf6d,0xbf803e163f73bef1,0x3ee63f4ebf39bf0e,0xbe603f80bdfbbf75,0x3f77bedbbf513f35,0x3f6a3e79bf7f3dc9,
0x3f0ebf6dbe483f80,0x3f7bbec4bf553f35,0x3f553ec4bf7b0000,0x3e483f6dbf0ebf35,0xbf0e3f6d3e48bf80,0xbf7b3ec43f55bf35,0xbf55bec43f7b0000,0xbe48bf6d3f0e3f35,
0x3f553ec4bf7b8000,0x3e483f6dbf0ebf35,0xbf0e3f6d3e48bf80,0xbf7b3ec43f55bf35,0xbf55bec43f7b8000,0xbe48bf6d3f0e3f35,0x3f0ebf6dbe483f80,0x3f7bbec4bf553f35,
0xbd973f7dbeb8bf55,0xbf513f3e3efcbf75,0x3f7ebeacbf583f35,0x3f393f04bf73bdc9,0x3ee6bf78bcc93f7b,0x3f7abedbbf4a3f46,0xbf77bd493f7cbec4,0xbecfbf4e3f423ef1,
0xbf7f3e163f6fbf0e,0xbf13bf2c3f5f3e95,0x3dfb3f71bf09bf35,0xbf313f5c3ea1bf7f,0x3f653e79bf803e48,0x3e603f67bf1dbf22,0x3e89bf803e2f3f6d,0x3f6abf18bf273f62,
0xbd49bf753f043f35,0x3f4ebf46bedb3f7b,0x3f713dc9bf7d3ec4,0x3e793f62bf2cbf0e,0x3f3e3ef1bf780000,0xbe163f7fbeacbf55,0xbf673f223f18bf6d,0xbf5cbe953f80be48,
0x3f80be95bf5c3f35,0x3f183f22bf67be48,0xbeac3f7fbe16bf6d,0xbf783ef13f3ebf55,0xbf2c3f623e79bf80,0xbf7d3dc93f71bf0e,0xbedbbf463f4e3ec4,0x3f04bf75bd493f7b,
0xbe603f80bea1bf55,0xbf773f043f31bf62,0x3f6fbf18bf1d3f6d,0x3f423edbbf7c3dc9,0xbf51beac3f7fbe48,0x3dfbbf7d3ecf3f46,0xbcc93f78befcbf35,0xbf653f2c3f09bf75,
0xbf7a3d493f73bf0e,0xbe89bf5c3f393ef1,0x3eb83f4ebf4abec4,0xbf273f673e2fbf7f,0x3f13bf71bd973f7b,0x3f7ebe16bf6a3f22,0xbf803e793f5fbf35,0xbee6bf3e3f583e95,
0xbf463f553e95bf80,0xbf62be483f7fbec4,0x3dc9bf7b3ef13f35,0x3f75bf0ebf223f6d,0x3f223f0ebf750000,0xbef13f7bbdc9bf6d,0xbf7f3e483f62bf35,0xbe95bf553f463ec4,
0xbf22bf0e3f758000,0x3ef1bf7b3dc93f6d,0x3f7fbe48bf623f35,0x3e953f55bf46bec4,0xbf463f553e95bf80,0xbf62be483f7fbec4,0x3dc9bf7b3ef13f35,0x3f75bf0ebf223f6d,
0x3f6abf2cbefc3f7b,0x3f273f04bf7a3dc9,0xbf7c3e163f65bf35,0xbdfbbf673f313ef1,0xbcc9bf713f1d3f0e,0x3f73bf18bf133f75,0xbf093f78bd97bf6d,0xbf773d493f6fbf22,
0x3ecf3f3ebf5fbe48,0xbf423f5c3e60bf7f,0x3e2fbf7d3ee63f35,0x3f7ebedbbf393f62,0x3f80beacbf4a3f55,0x3ea13f4ebf51be95,0xbf58be793f7fbec4,0x3e89bf803eb83f46,
0xbf783dc93f67bf35,0x3d49bf753f183f0e,0x3f7dbef1bf2c3f6d,0x3eac3f46bf5cbe48,0xbf04bf223f710000,0x3f3ebf62be163f7b,0x3f4e3e95bf803ec4,0xbedb3f7fbe79bf55,
0x3e79bf7f3edb3f35,0x3f80be95bf4e3f55,0x3e163f62bf3ebec4,0xbf713f223f04bf7b,0x3f5cbf46beac3f80,0x3f2c3ef1bf7d3e48,0xbf183f75bd49bf6d,0xbf67bdc93f78bf0e,
0x3e893f4ebf58be48,0xbf6f3f2c3ee6bf7f,0xbd97bf673f393ec4,0x3f7cbf04bf1d3f75,0xbdfb3f78bf13bf0e,0xbf803eac3f42bf62,0x3ea1bf803ecf3f35,0x3f7abe16bf5f3f46,
0xbf773f183f09bf7b,0xbeb8bf3e3f653dc9,0x3f7fbedbbf313f6d,0x3e2f3f5cbf4abe95,0xbf7e3e793f51bf55,0x3cc9bf713f273ef1,0x3f73bd49bf6a3f35,0xbe603f7dbefcbf22,
0x3f6dbf35bec43f80,0x3ec43f35bf6d0000,0xbf6d3f353ec4bf80,0xbec4bf353f6d0000,0x3f6dbf35bec43f80,0x3ec43f35bf6d0000,0xbf6d3f353ec4bf80,0xbec4bf353f6d0000,
0x3ec43f35bf6d8000,0xbf6d3f353ec4bf80,0xbec4bf353f6d8000,0x3f6dbf35bec43f80,0x3ec43f35bf6d8000,0xbf6d3f353ec4bf80,0xbec4bf353f6d8000,0x3f6dbf35bec43f80,
0xbf4abe793f7cbf0e,0x3f31bf713d973f62,0x3f653d49bf6f3f35,0xbf093f7dbe89bf46,0xbefcbf183f7abe48,0x3f6abf3ebea13f7f,0x3f273edbbf803ec4,0xbf513f5c3dfbbf75,
0x3f1dbf783e2f3f55,0x3f393eacbf7f3ef1,0xbee63f80beb8bf35,0xbf58be163f77bf22,0x3f5fbf4ebe603f7b,0x3ecf3f2cbf733dc9,0xbf423f673cc9bf6d,0xbf13bf043f7ebe95,
0xbf043f7fbeacbf35,0xbf3ebe953f7dbf0e,0x3f4ebf62bd493f6d,0x3edb3f22bf783e48,0x3e793f46bf670000,0xbf803ef13f18bf7b,0x3e16bf753f2c3ec4,0x3f71bdc9bf5c3f55,
0xbf5cbdc93f71bf35,0x3f2cbf753e163f55,0x3f183ef1bf803ec4,0xbf673f463e79bf7b,0xbf783f223edbbf80,0xbd49bf623f4e3e48,0x3f7dbe95bf3e3f6d,0xbeac3f7fbf04bf0e,
0x3f313eacbf7e3f0e,0xbf653f4e3e2fbf75,0xbf7a3e793f42bf6d,0x3efcbf803ecf3f22,0x3f6fbf3ebe893f7b,0x3d973f5cbf58bdc9,0xbf133f7dbea1bf35,0xbf1dbedb3f80bef1,
0xbf393f71bdfbbf55,0xbee6bf183f7cbe95,0x3e60bf783f273ec4,0x3f5f3d49bf6a3f46,0x3eb83f2cbf773e48,0xbf7f3f043f09bf7f,0xbf51be163f73bf35,0x3f4abf673cc93f62,
0xbf7f3f0e3ef1bf80,0x3e95bf7b3f223ec4,0x3f463e48bf753f35,0xbf623f553dc9bf6d,0xbdc9bf553f620000,0x3f75be48bf463f6d,0xbf223f7bbe95bf35,0xbef1bf0e3f7fbec4,
0xbdc9bf553f628000,0x3f75be48bf463f6d,0xbf223f7bbe95bf35,0xbef1bf0e3f7fbec4,0x3f7fbf0ebef13f80,0xbe953f7bbf22bec4,0xbf46be483f75bf35,0x3f62bf55bdc93f6d,
0xbe2f3f71bf42be48,0xbf4abe163f6fbf46,0xbf39be793f77bf35,0x3f73bf3ebe603f75,0xbf58bd493f65bf55,0x3f5fbf5cbcc93f62,0x3f6abf4ebdfb3f6d,0xbd973f67bf51bdc9,
0xbf7c3eac3f27bf7b,0x3f1dbf7d3eb83f22,0x3f31bf783e893f35,0x3ea13f2cbf7a3e95,0x3f09bf803ee63f0e,0x3efc3f04bf803ef1,0x3ecf3f18bf7e3ec4,0xbf7f3edb3f13bf7f,
0x3f2c3e95bf783f35,0xbf7d3f223eacbf7b,0x3edbbf7f3f183ec4,0x3f043ef1bf803f0e,0x3d49bf623f5c0000,0x3f4e3dc9bf673f55,0xbf713f463e16bf6d,0x3e79bf753f3e3e48,
0xbf3e3f75be79bf35,0xbe16bf463f71be48,0x3f67bdc9bf4e3f6d,0xbf5c3f62bd49bf55,0x3f80bef1bf043f80,0xbf183f7fbedbbf0e,0xbeacbf223f7dbec4,0x3f78be95bf2c3f7b,
0x3f73be79bf313f7b,0xbf583f67bdfbbf46,0xbefc3f80bf13bec4,0xbeb8bf183f7fbef1,0xbf42be163f6abf55,0x3f7cbf2cbe893f75,0x3f4abf713e603f35,0xbcc93f5cbf653dc9,
0xbea13f78bf39be48,0xbf09bedb3f7ebf22,0xbf5f3d493f51bf6d,0x3f6fbf4ebd973f62,0x3f27bf7d3ecf3f0e,0x3e2f3f3ebf773e95,0x3f1d3eacbf7a3f35,0xbf803f043ee6bf7f,
0x3f7bbec4bf0e3f80,0xbf553f6dbe48bf35,0x3e48bf6d3f550000,0x3f0e3ec4bf7b3f35,0xbf7b3ec43f0ebf80,0x3f55bf6d3e483f35,0xbe483f6dbf550000,0xbf0ebec43f7bbf35,
0xbe483f6dbf558000,0xbf0ebec43f7bbf35,0x3f7bbec4bf0e3f80,0xbf553f6dbe48bf35,0x3e48bf6d3f558000,0x3f0e3ec4bf7b3f35,0xbf7b3ec43f0ebf80,0x3f55bf6d3e483f35,
0x3f73bf4ebcc93f55,0xbf093f80bf1dbe95,0x3efc3edbbf7c3f35,0xbf6f3e793f27bf7f,0xbf7f3f043ecfbf7b,0x3f51bf713e893f22,0xbdfbbf3e3f7abec4,0x3f393e16bf653f62,
0x3ea13f18bf803f0e,0xbf583d493f4abf75,0xbf5f3f67be2fbf35,0x3eb8bf783f423dc9,0x3d97bf5c3f6abe48,0x3f133eacbf773f46,0x3f7ebf2cbe603f6d,0xbf313f7dbee6bef1,
0x3f67bf623e163f35,0xbf043f7fbf2cbe48,0xbd49bf463f78bec4,0x3f183e95bf713f55,0xbeac3f75bf4e0000,0xbe79bf223f80bf0e,0x3f3e3dc9bf5c3f6d,0xbf7d3ef13edbbf7b,
0x3edb3ef1bf7d3f35,0xbf5c3dc93f3ebf7b,0x3f80bf22be793f6d,0xbf4e3f75beacbf0e,0xbf713e953f18bf80,0x3f78bf46bd493f55,0xbf2c3f7fbf04bec4,0x3e16bf623f67be48,
0x3f7cbf3ebd973f55,0xbf4a3f78becfbef1,0x3f313e16bf5f3f6d,0xbf733eac3f09bf7f,0xbe603f67bf653e48,0xbe89bf183f80bf22,0xbf6f3f5cbdfbbf35,0x3f27bf803f133e95,
0x3e2f3f2cbf7f3f0e,0xbf1dbe793f6abf62,0xbf393f7dbefcbec4,0x3ea1bf713f58bdc9,0xbf7a3edb3ee6bf7b,0x3f77bf4e3cc93f46,0xbeb8bf043f7ebf35,0x3f423d49bf513f75,
0xbf623e483f22bf80,0x3f7fbf0ebe953f6d,0xbf753f55bdc9bf35,0x3f46bf7b3ef13ec4,0xbef13f7bbf460000,0x3dc9bf553f75bec4,0x3e953f0ebf7f3f35,0xbf22be483f62bf6d,
0x3ef1bf7b3f468000,0xbdc93f55bf753ec4,0xbe95bf0e3f7fbf35,0x3f223e48bf623f6d,0xbf623e483f22bf80,0x3f7fbf0ebe953f6d,0xbf753f55bdc9bf35,0x3f46bf7b3ef13ec4,
0xbf39bd493f4abf7b,0x3f65be79bf133f7f,0xbe60bf183f7fbf35,0x3efc3eacbf6f3f62,0xbf6a3f67be89bf0e,0x3f42bf7d3f093e95,0xbf7c3f043ea1bf6d,0x3f7ebf3ebcc93f46,
0x3f31bf803f1d3e48,0xbee63f78bf513dc9,0x3f7abf4e3d973f35,0xbf5f3f71beb8bef1,0xbecfbedb3f77bf55,0x3f273e16bf583f75,0x3e2fbf5c3f73bec4,0x3dfb3f2cbf803f22,
0xbe16bf223f80bf35,0x3eac3ef1bf783f55,0xbf04be953f67bf6d,0x3f2c3dc9bf4e3f7b,0x3f18bf7f3f3e0000,0xbedb3f75bf5c3e48,0x3e79bf623f71bec4,0xbd493f46bf7d3f0e,
0x3f7dbf463d493f35,0xbf713f62be79bf0e,0x3f5cbf753edb3ec4,0xbf3e3f7fbf18be48,0x3f4ebdc9bf2c3f80,0xbf673e953f04bf7b,0x3f78bef1beac3f6d,0xbf803f223e16bf55,
0x3f4abf7d3f133e48,0xbf393f80bf27bdc9,0x3f65bf713ecf3ec4,0xbf583f78befcbe95,0x3f77bf5c3e603f0e,0xbf6f3f67bea1bef1,0x3f7fbf3e3cc93f35,0xbf7c3f4ebdfbbf22,
0x3f1d3e16bf513f7b,0xbf31bd493f42bf7f,0x3ee63eacbf6a3f6d,0xbf09be793f5fbf75,0x3e893f04bf7a3f55,0xbeb8bedb3f73bf62,0x3d973f2cbf803f35,0xbe2fbf183f7ebf46,
0xbf3500003f353f80,0x3f350000bf35bf80,0xbf3500003f353f80,0x3f350000bf35bf80,0xbf3500003f353f80,0x3f350000bf35bf80,0xbf3500003f353f80,0x3f350000bf35bf80,
0xbf35bf80bf358000,0x3f353f803f358000,0xbf35bf80bf358000,0x3f353f803f358000,0xbf35bf80bf358000,0x3f353f803f358000,0xbf35bf80bf358000,0x3f353f803f358000,
0xbf773f78bf7a3f7b,0xbf6f3f71bf733f75,0xbf7f3f80bf803f80,0xbf7c3f7dbf7e3f7f,0xbf4a3f4ebf513f55,0xbf393f3ebf423f46,0xbf653f67bf6a3f6d,0xbf583f5cbf5f3f62,
0x3e89be793e60be48,0x3eb8beac3ea1be95,0x3d97bd493cc98000,0x3e2fbe163dfbbdc9,0x3f1dbf183f13bf0e,0x3f31bf2c3f27bf22,0x3ee6bedb3ecfbec4,0x3f09bf043efcbef1,
0xbf183f22bf2c3f35,0xbedb3ef1bf043f0e,0xbe793e95beac3ec4,0xbd493dc9be163e48,0xbf7d3f7fbf803f80,0xbf713f75bf783f7b,0xbf5c3f62bf673f6d,0xbf3e3f46bf4e3f55,
0x3f4ebf463f3ebf35,0x3f67bf623f5cbf55,0x3f78bf753f71bf6d,0x3f80bf7f3f7dbf7b,0x3e16bdc93d498000,0x3eacbe953e79be48,0x3f04bef13edbbec4,0x3f2cbf223f18bf0e,
0x3ecfbeac3e89be48,0x3f27bf183f09bef1,0xbe2f3e79bea13ec4,0x3dfbbd49bcc93dc9,0xbf313f3ebf4a3f55,0xbee63f04bf133f22,0xbf7a3f7dbf7f3f80,0xbf5f3f67bf6f3f75,
0x3f6abf713f77bf7b,0x3f42bf4e3f58bf62,0x3f7cbf783f73bf6d,0x3f7ebf803f80bf7f,0x3f39bf2c3f1dbf0e,0x3f65bf5c3f51bf46,0x3e60be163d978000,0x3efcbedb3eb8be95,
0xbf753f7bbf7f3f80,0xbf463f55bf623f6d,0xbef13f0ebf223f35,0xbdc93e48be953ec4,0x3e95be483dc90000,0x3f22bf0e3ef1bec4,0x3f62bf553f46bf35,0x3f7fbf7b3f75bf6d,
0x3e95be483dc98000,0x3f22bf0e3ef1bec4,0x3f62bf553f46bf35,0x3f7fbf7b3f75bf6d,0x3f75bf7b3f7fbf80,0x3f46bf553f62bf6d,0x3ef1bf0e3f22bf35,0x3dc9be483e95bec4,
0xbe603eacbee63f0e,0x3e89be163cc93dc9,0xbf6f3f78bf7e3f80,0xbf273f3ebf513f62,0x3f7cbf803f7fbf7b,0x3f4abf5c3f6abf75,0x3f31bf183efcbec4,0x3f73bf673f58bf46,
0x3f7abf713f65bf55,0x3f77bf7d3f80bf7f,0x3eb8be793dfb8000,0x3f42bf2c3f13bef1,0xbe2f3d493d97be48,0xbf1d3f04becf3e95,0x3f39bf4e3f5fbf6d,0x3ea1bedb3f09bf22,
0x3f71bf623f4ebf35,0x3f78bf7f3f80bf7b,0x3f2cbf463f5cbf6d,0x3e16be953edbbf0e,0xbf673f75bf7d3f80,0xbf043f22bf3e3f55,0x3d493dc9be793ec4,0x3f18bef13eacbe48,
0x3eacbef13f18bf35,0xbe793dc93d49be48,0xbf3e3f22bf043ec4,0xbf7d3f75bf673f55,0x3edbbe953e168000,0x3f5cbf463f2cbf0e,0x3f80bf7f3f78bf6d,0x3f4ebf623f71bf7b,
0x3d97be793ecfbf0e,0xbf133edbbe893dc9,0x3f7ebf803f7abf6d,0x3f31bf4e3f65bf75,0x3ea1be16bcc93e48,0x3f58bf3e3f1dbef1,0xbf5f3f71bf7c3f80,0xbeb83f04bf273f46,
0xbf7f3f78bf6a3f55,0xbf513f67bf773f7f,0xbdfbbd493e60bec4,0xbf393f18bee63e95,0x3f73bf7d3f80bf7b,0x3f09bf2c3f4abf62,0x3efcbeac3e2f8000,0x3f6fbf5c3f42bf22,
0xbf553f6dbf7b3f80,0xbe483ec4bf0e3f35,0x3f0ebec43e480000,0x3f7bbf6d3f55bf35,0x3f55bf6d3f7bbf80,0x3e48bec43f0ebf35,0xbf0e3ec4be480000,0xbf7b3f6dbf553f35,
0x3f0ebec43e488000,0x3f7bbf6d3f55bf35,0x3f55bf6d3f7bbf80,0x3e48bec43f0ebf35,0xbf0e3ec4be488000,0xbf7b3f6dbf553f35,0xbf553f6dbf7b3f80,0xbe483ec4bf0e3f35,
0x3f42bf183ecfbe48,0x3f7cbf803f77bf62,0xbf4a3f67bf7a3f80,0xbcc93e79bee63f22,0xbf733f5cbf393f0e,0xbf583f71bf7e3f7f,0x3efcbf2c3f51bf6d,0xbeb83e163d97be95,
0x3f27bf4e3f6abf7b,0xbe2fbd493e89bef1,0x3f1dbedb3e608000,0x3f80bf783f65bf46,0xbea13f04bf313f55,0x3f09beac3dfb3dc9,0xbf5f3f3ebf133ec4,0xbf6f3f7dbf7f3f75,
0x3d49be953f04bf35,0xbf4e3f22bedb3e48,0xbf713f7fbf7d3f6d,0xbe793ef1bf2c3f55,0xbf3e3f62bf783f80,0x3e163dc9beac3f0e,0x3f67bf463f18bec4,0x3f5cbf753f80bf7b,
0xbf803f75bf5c3f35,0xbf183f46bf673f7b,0x3eacbdc9be163ec4,0x3f78bf623f3ebf0e,0x3f2cbef13e798000,0x3f7dbf7f3f71bf55,0x3edbbf223f4ebf6d,0xbf043e95bd49be48,
0xbf093f3ebf653f7b,0x3efcbe79bcc93e95,0xbecf3e163dfbbec4,0xbf7f3f71bf513f22,0x3f7cbf673f42bf0e,0x3f1dbf4e3f6fbf7f,0xbf313f5cbf773f80,0x3ea1bd49be603ef1,
0x3f58bf2c3ee6be48,0x3f5fbf783f80bf75,0xbf6a3f7dbf7e3f6d,0xbd973eacbf133f46,0x3e2fbedb3f27bf55,0xbf4a3f18beb83dc9,0x3f39bf043e898000,0x3f73bf803f7abf62,
0xbf223f55bf753f80,0x3ef1be48bdc93ec4,0x3f7fbf7b3f62bf35,0x3e95bf0e3f46bf6d,0xbf463f0ebe950000,0xbf623f7bbf7f3f6d,0x3dc93e48bef13f35,0x3f75bf553f22bec4,
0x3f46bf0e3e958000,0x3f62bf7b3f7fbf6d,0xbdc9be483ef1bf35,0xbf753f55bf223ec4,0xbf223f55bf753f80,0x3ef1be48bdc93ec4,0x3f7fbf7b3f62bf35,0x3e95bf0e3f46bf6d,
0x3f6fbf803f77bf55,0xbd97be793f09bf46,0xbf133f4ebf733f80,0x3f1dbeac3cc93e95,0x3f31bedb3dfb3e48,0x3f65bf7d3f7cbf62,0xbf7a3f5cbf273ec4,0xbefc3f3ebf6a3f7f,
0xbeb83d493e89bf0e,0xbf7f3f78bf583f22,0x3f51bf183ea18000,0x3f4abf713f80bf75,0x3f39bf673f7ebf7b,0xbee63e163e2fbef1,0xbe603f04bf423f6d,0x3f5fbf2c3ecfbdc9,
0xbf783f7fbf673f35,0x3d493e95bf183f55,0x3f7dbf623f2cbec4,0x3eacbf223f5cbf7b,0xbf043f46bf713f80,0x3f3ebef13e163e48,0x3f4ebf753f80bf6d,0xbedb3dc93e79bf0e,
0x3e793dc9bedb3f35,0x3f80bf753f4ebf0e,0x3e16bef13f3ebf6d,0xbf713f46bf043e48,0x3f5cbf223eac8000,0x3f2cbf623f7dbf7b,0xbf183e953d49bec4,0xbf673f7fbf783f55,
0x3f5fbf7d3f7abf55,0xbecf3d493ea1bf22,0xbf423f71bf803f6d,0x3f13be79bdfb3ef1,0x3f1dbf5c3f7cbf7b,0xbf393edbbd97be95,0xbee63f3ebf6f3f80,0x3f58bf183e893dc9,
0xbefc3e163e60bf0e,0xbf6a3f80bf733f46,0x3f27beacbcc93ec4,0x3f51bf783f7ebf62,0xbf4a3f04be2fbe48,0xbf313f67bf7f3f75,0x3f65bf2c3eb88000,0x3f09bf4e3f77bf7f,
0xbec43f35bf6d3f80,0x3f6dbf353ec40000,0x3ec4bf353f6dbf80,0xbf6d3f35bec40000,0xbec43f35bf6d3f80,0x3f6dbf353ec40000,0x3ec4bf353f6dbf80,0xbf6d3f35bec40000,
0x3f6dbf353ec48000,0x3ec4bf353f6dbf80,0xbf6d3f35bec48000,0xbec43f35bf6d3f80,0x3f6dbf353ec48000,0x3ec4bf353f6dbf80,0xbf6d3f35bec48000,0xbec43f35bf6d3f80,
0x3dfbbf043f51bf7b,0xbf803f67bf273e95,0xbea13f2cbf6a3f80,0x3f7abf4e3efcbdc9,0xbe89be163f09bf55,0xbf6f3f80bf653f22,0x3d973eacbf313f6d,0x3f7cbf783f4abef1,
0xbf7e3f5cbf133e48,0xbcc93edbbf423f75,0x3f73bf3e3ecf8000,0x3e60bf183f5fbf7f,0xbf773f7dbf583f0e,0x3eb83d49bee63f46,0x3f7fbf713f39bec4,0xbe2fbe793f1dbf62,
0x3f04bdc9beac3f35,0x3f3ebf753f7dbf55,0xbf4e3ef1bd49bec4,0xbedb3f46bf783f7b,0xbe793f22bf673f80,0x3f80bf623f18be48,0xbe16be953f2cbf6d,0xbf713f7fbf5c3f0e,
0x3f5cbf7f3f71bf35,0xbf2c3e953e16bf0e,0xbf183f62bf803f6d,0x3f67bf223e793e48,0x3f78bf463edb8000,0x3d49bef13f4ebf7b,0xbf7d3f75bf3e3ec4,0x3eac3dc9bf043f55,
0xbf803f67bf1d3e48,0x3ea13e16bf133f62,0x3f58bf043d973ec4,0x3e89bf2c3f6fbf7f,0xbecfbd493efcbf55,0xbf423f78bf7a3f46,0xbe2f3f18bf653f80,0x3f7ebf713f31be95,
0x3cc93edbbf4a3f7b,0x3f73bf7d3f51bef1,0x3f09bf5c3f7fbf6d,0xbf773f3ebeb8bdc9,0xbf6a3f80bf5f3f0e,0x3f27be79be603f22,0x3f7cbf4e3ee68000,0xbdfbbeac3f39bf75,
0xbdc93f0ebf623f80,0x3f75bf7b3f46bec4,0xbf223e483e95bf35,0xbef13f55bf7f3f6d,0x3f7fbf553ef10000,0xbe95be483f22bf6d,0xbf463f7bbf753f35,0x3f62bf0e3dc93ec4,
0x3f7fbf553ef18000,0xbe95be483f22bf6d,0xbf463f7bbf753f35,0x3f62bf0e3dc93ec4,0x3dc9bf0e3f62bf80,0xbf753f7bbf463ec4,0x3f22be48be953f35,0x3ef1bf553f7fbf6d,
0xbf513edb3d97bf0e,0xbdfb3f18bf6a3f7f,0xbcc93f04bf5f3f80,0x3f65bf803f58bef1,0xbe603f2cbf733f7b,0x3f77bf783f39be95,0x3f6fbf7d3f4abec4,0xbf423eac3e2fbf22,
0xbf133f67bf7f3f55,0x3f7ebf4e3ecf3dc9,0x3f80bf5c3efc8000,0xbee6bd493f09bf62,0x3f7abf3e3ea13e48,0xbe89be793f31bf75,0xbeb8be163f1dbf6d,0xbf273f71bf7c3f46,
0x3f2cbf753f78bf35,0xbf7d3f46beacbe48,0x3edb3dc9bf183f6d,0x3f04bf623f80bf55,0x3d493ef1bf5c3f80,0x3f4ebf7f3f67bf0e,0xbf713f22be16bec4,0x3e793e95bf3e3f7b,
0xbf3e3e953e79bf35,0xbe163f22bf713f7b,0x3f67bf7f3f4ebec4,0xbf5c3ef13d49bf0e,0x3f80bf623f048000,0xbf183dc93edbbf55,0xbeac3f46bf7d3f6d,0x3f78bf753f2cbe48,
0x3f65bf04bcc93f0e,0xbe60beac3f4abf7f,0x3e89bf3e3f7cbf6d,0xbf6a3f7dbf423e95,0xbf7f3f4ebeb8be48,0x3f13bd49befc3f62,0x3dfb3edbbf583f80,0x3f31bf783f73bf22,
0x3ee6bf5c3f80bf55,0xbf7a3f71bf1d3dc9,0xbf773f2cbe2fbec4,0x3ecf3e16bf273f75,0xbd973f18bf6f3f7b,0x3f51bf803f5fbef1,0x3f7ebf673f098000,0xbf393e793ea1bf46,
0x3e483ec4bf553f80,0x3f0ebf6d3f7bbf35,0xbf7b3f6dbf0e0000,0x3f55bec4be483f35,0xbe48bec43f55bf80,0xbf0e3f6dbf7b3f35,0x3f7bbf6d3f0e0000,0xbf553ec43e48bf35,
0x3f7bbf6d3f0e8000,0xbf553ec43e48bf35,0x3e483ec4bf553f80,0x3f0ebf6d3f7bbf35,0xbf7b3f6dbf0e8000,0x3f55bec4be483f35,0xbe48bec43f55bf80,0xbf0e3f6dbf7b3f35,
0xbf653f7dbf393e48,0x3f7abf2c3dfb3ef1,0x3e893eacbf513f80,0x3ecfbf5c3f7fbf46,0x3f27bf783f6fbf0e,0xbf7c3f67befcbdc9,0xbf1d3d493f09bf6d,0xbcc93f18bf733f75,
0x3ee63e16bf313f7b,0x3e60bf3e3f7ebf62,0x3f77bf713f138000,0xbf6a3f043d97bf22,0xbf423e793eb8bf55,0x3e2f3edbbf5f3f7f,0xbf4a3f80bf583ec4,0x3f80bf4e3ea13e95,
0xbf673ef13e16bf35,0x3f043dc9bf2c3f7b,0x3d49bf223f78bf6d,0xbf183f75bf713f0e,0x3eac3e95bf4e3f80,0x3e79bf463f80bf55,0xbf3e3f7fbf5c3ec4,0x3f7dbf623edb3e48,
0xbedb3f62bf7d3f35,0x3f5cbf7f3f3ebe48,0xbf803f46be79bec4,0x3f4ebe95beac3f55,0x3f71bf753f188000,0xbf783f22bd49bf0e,0x3f2cbdc9bf043f6d,0xbe16bef13f67bf7b,
0xbf13bd493f27bf7b,0x3dfb3f04bf6f3f75,0xbf803f4ebe89bec4,0x3f65bedbbe603f46,0xbf093f71bf733f0e,0x3f5fbf7d3f31bdc9,0x3ecf3e79bf4a3f80,0x3d97bf2c3f7cbf62,
0xbf513f80bf423e48,0x3f7ebf5c3eb83e95,0x3cc93f18bf773f6d,0x3ee6bf673f7abf22,0x3f58beacbea13f55,0xbefcbe163f39bf7f,0x3f6abf783f1d8000,0xbf7f3f3ebe2fbef1,
0x3ef13e48bf463f80,0xbdc9bf0e3f75bf6d,0xbe953f55bf7f3f35,0x3f22bf7b3f62bec4,0xbf623f7bbf220000,0x3f7fbf553e953ec4,0xbf753f0e3dc9bf35,0x3f46be48bef13f6d,
0x3f62bf7b3f228000,0xbf7f3f55be95bec4,0x3f75bf0ebdc93f35,0xbf463e483ef1bf6d,0x3ef13e48bf463f80,0xbdc9bf0e3f75bf6d,0xbe953f55bf7f3f35,0x3f22bf7b3f62bec4,
0xbcc93f2cbf7e3f55,0x3ea1bf5c3f7cbf22,0x3f093e16bf423f80,0xbe89bedb3f6abf75,0xbf6f3f71befcbe48,0x3f7fbf4e3e603ef1,0xbf133f78bf653ec4,0x3f4abf803f39bdc9,
0x3f80bf3e3dfb3f0e,0xbf733f043e2fbf46,0x3f58bf7d3f278000,0xbf773f67becfbe95,0x3eb83eacbf5f3f7b,0xbd97bf183f7abf62,0x3f51be79bee63f6d,0xbf1dbd493f31bf7f,
0xbe163f46bf803f35,0x3eacbf623f78bf0e,0xbf043f75bf673ec4,0x3f2cbf7f3f4ebe48,0x3f183dc9bf3e3f80,0xbedbbe953f5cbf7b,0x3e793ef1bf713f6d,0xbd49bf223f7dbf55,
0x3f7dbf22bd493f35,0xbf713ef13e79bf55,0x3f5cbe95bedb3f6d,0xbf3e3dc93f18bf7b,0x3f4ebf7f3f2c8000,0xbf673f75bf04be48,0x3f78bf623eac3ec4,0xbf803f46be16bf0e,
0x3dfb3f18bf7c3f55,0xbcc9bf2c3f7fbf46,0x3ea13edbbf6f3f6d,0xbe60bf043f77bf62,0x3efc3e79bf583f7b,0xbecfbeac3f65bf75,0x3f273d49bf393f80,0xbf13be163f4abf7f,
0x3f7ebf4e3e2f3f0e,0xbf803f3ebd97bf22,0x3f73bf673eb83ec4,0xbf7a3f5cbe89bef1,0x3f5fbf783f093e48,0xbf6a3f71bee6be95,0x3f42bf803f318000,0xbf513f7dbf1dbdc9,
0xbf3500003f353f80,0x3f350000bf35bf80,0xbf3500003f353f80,0x3f350000bf35bf80,0xbf3500003f353f80,0x3f350000bf35bf80,0xbf3500003f353f80,0x3f350000bf35bf80,
0xbf35bf80bf358000,0x3f353f803f358000,0xbf35bf80bf358000,0x3f353f803f358000,0xbf35bf80bf358000,0x3f353f803f358000,0xbf35bf80bf358000,0x3f353f803f358000,
0xbefc3f04bf093f0e,0xbecf3edbbee63ef1,0xbf273f2cbf313f35,0xbf133f18bf1d3f22,0xbdfb3e16be2f3e48,0xbcc93d49bd973dc9,0xbea13eacbeb83ec4,0xbe603e79be893e95,
0x3f5fbf5c3f58bf55,0x3f6abf673f65bf62,0x3f42bf3e3f39bf35,0x3f51bf4e3f4abf46,0x3f7ebf7d3f7cbf7b,0x3f80bf803f7fbf7f,0x3f73bf713f6fbf6d,0x3f7abf783f77bf75,
0x3f4ebf463f3ebf35,0x3f67bf623f5cbf55,0x3f78bf753f71bf6d,0x3f80bf7f3f7dbf7b,0x3e16bdc93d490000,0x3eacbe953e79be48,0x3f04bef13edbbec4,0x3f2cbf223f18bf0e,
0x3f18bf223f2cbf35,0x3edbbef13f04bf0e,0x3e79be953eacbec4,0x3d49bdc93e16be48,0x3f7dbf7f3f80bf80,0x3f71bf753f78bf7b,0x3f5cbf623f67bf6d,0x3f3ebf463f4ebf55,
0x3eb8bedb3efcbf0e,0x3d97be163e60be95,0x3f51bf5c3f65bf6d,0x3f1dbf2c3f39bf46,0x3f80bf803f7ebf7b,0x3f73bf783f7cbf7f,0x3f58bf4e3f42bf35,0x3f77bf713f6abf62,
0xbf6f3f67bf5f3f55,0xbf7f3f7dbf7a3f75,0xbf133f04bee63ec4,0xbf4a3f3ebf313f22,0xbcc9bd493dfbbe48,0xbea13e79be2f3dc9,0x3f09bf183f27bf35,0x3e89beac3ecfbef1,
0x3f75bf7b3f7fbf80,0x3f46bf553f62bf6d,0x3ef1bf0e3f22bf35,0x3dc9be483e95bec4,0xbe953e48bdc90000,0xbf223f0ebef13ec4,0xbf623f55bf463f35,0xbf7f3f7bbf753f6d,
0xbe953e48bdc98000,0xbf223f0ebef13ec4,0xbf623f55bf463f35,0xbf7f3f7bbf753f6d,0xbf753f7bbf7f3f80,0xbf463f55bf623f6d,0xbef13f0ebf223f35,0xbdc93e48be953ec4,
0xbf093edbbea13e48,0xbf5f3f4ebf393f22,0x3ecfbf043f1dbf35,0xbd97bd493e2fbe95,0xbf133f2cbf423f55,0xbdfb3e79beb83ef1,0xbf803f7dbf773f6d,0xbf653f71bf7a3f7f,
0xbf583f67bf733f7b,0xbefc3f18bf313f46,0xbf6a3f5cbf4a3f35,0xbf7f3f80bf7c3f75,0x3f51bf3e3f27bf0e,0x3f7ebf783f6fbf62,0xbcc93e16be893ec4,0x3ee6beac3e60bdc9,
0xbeac3ef1bf183f35,0x3e79bdc9bd493e48,0x3f3ebf223f04bec4,0x3f7dbf753f67bf55,0xbedb3e95be160000,0xbf5c3f46bf2c3f0e,0xbf803f7fbf783f6d,0xbf4e3f62bf713f7b,
0x3f71bf623f4ebf35,0x3f78bf7f3f80bf7b,0x3f2cbf463f5cbf6d,0x3e16be953edbbf0e,0xbf673f75bf7d3f80,0xbf043f22bf3e3f55,0x3d493dc9be793ec4,0x3f18bef13eacbe48,
0x3f42bf5c3f6fbf7b,0x3e2fbeac3efcbf22,0x3f4abf2c3f09bec4,0x3f80bf7d3f73bf62,0xbee63f18bf393f55,0x3e60bd49bdfb3e95,0xbf773f67bf513f35,0xbf6a3f78bf7f3f7f,
0xbf273f04beb83e48,0xbf7c3f71bf5f3f46,0x3f1dbf3e3f58bf6d,0xbcc9be163ea1bef1,0x3f65bf4e3f31bf0e,0x3f7abf803f7ebf75,0xbe893edbbf133f35,0x3ecfbe793d973dc9,
0xbf553f6dbf7b3f80,0xbe483ec4bf0e3f35,0x3f0ebec43e480000,0x3f7bbf6d3f55bf35,0x3f55bf6d3f7bbf80,0x3e48bec43f0ebf35,0xbf0e3ec4be480000,0xbf7b3f6dbf553f35,
0x3f0ebec43e488000,0x3f7bbf6d3f55bf35,0x3f55bf6d3f7bbf80,0x3e48bec43f0ebf35,0xbf0e3ec4be488000,0xbf7b3f6dbf553f35,0xbf553f6dbf7b3f80,0xbe483ec4bf0e3f35,
0x3f7fbf7d3f6fbf55,0x3f13bf3e3f5fbf75,0xbdfb3eacbf093f35,0x3f31bf043ea1bdc9,0xbf653f78bf803f7b,0xbe603edbbf1d3f46,0xbe893d493e2fbec4,0xbf6a3f4ebf273ef1,
0xbd97be163eb8bf0e,0xbf513f2cbefc3e95,0x3f7ebf713f58bf35,0x3f39bf5c3f73bf7f,0x3ee6be793cc93e48,0x3f7abf673f4abf22,0xbf773f80bf7c3f6d,0xbecf3f18bf423f62,
0xbf803f75bf5c3f35,0xbf183f46bf673f7b,0x3eacbdc9be163ec4,0x3f78bf623f3ebf0e,0x3f2cbef13e790000,0x3f7dbf7f3f71bf55,0x3edbbf223f4ebf6d,0xbf043e95bd49be48,
0xbd493e95bf043f35,0x3f4ebf223edbbe48,0x3f71bf7f3f7dbf6d,0x3e79bef13f2cbf55,0x3f3ebf623f78bf80,0xbe16bdc93eacbf0e,0xbf673f46bf183ec4,0xbf5c3f75bf803f7b,
0x3f7abf803f73bf55,0x3e89bf043f39bf62,0xbeb83f18bf4a3f6d,0x3f27bedb3e2f3dc9,0xbf133eacbd97be48,0xbf7e3f7dbf6a3f46,0x3f80bf783f5fbf35,0x3ee6bf2c3f58bf75,
0xbe60bd493ea1bf0e,0xbf773f5cbf313ef1,0x3f6fbf4e3f1dbec4,0x3f42bf673f7cbf7f,0xbf513f71bf7f3f7b,0x3dfb3e16becf3f22,0xbcc9be793efcbf35,0xbf653f3ebf093e95,
0x3f22bf553f75bf80,0xbef13e483dc9bec4,0xbf7f3f7bbf623f35,0xbe953f0ebf463f6d,0x3f46bf0e3e950000,0x3f62bf7b3f7fbf6d,0xbdc9be483ef1bf35,0xbf753f55bf223ec4,
0xbf463f0ebe958000,0xbf623f7bbf7f3f6d,0x3dc93e48bef13f35,0x3f75bf553f22bec4,0x3f22bf553f75bf80,0xbef13e483dc9bec4,0xbf7f3f7bbf623f35,0xbe953f0ebf463f6d,
0xbecf3f2cbf5f3f7b,0x3f42bf043e603dc9,0xbe2fbe163ee6bf35,0xbf7e3f67bf393ef1,0xbf803f71bf4a3f0e,0xbea13f18bf513f75,0x3f58bf783f7fbf6d,0xbe89bd493eb8bf22,
0x3f6abf3e3efcbe48,0x3f27bf5c3f7abf7f,0xbf7c3f7dbf653f35,0xbdfb3edbbf313f62,0xbcc93eacbf1d3f55,0x3f73bf4e3f13be95,0xbf093e793d97bec4,0xbf773f80bf6f3f46,
0xbe79bdc93edbbf35,0xbf803f75bf4e3f0e,0xbe163ef1bf3e3f6d,0x3f71bf463f04be48,0xbf5c3f22beac0000,0xbf2c3f62bf7d3f7b,0x3f18be95bd493ec4,0x3f67bf7f3f78bf55,
0xbf783f7fbf673f35,0x3d493e95bf183f55,0x3f7dbf623f2cbec4,0x3eacbf223f5cbf7b,0xbf043f46bf713f80,0x3f3ebef13e163e48,0x3f4ebf753f80bf6d,0xbedb3dc93e79bf0e,
0x3f77bf4e3f09be48,0x3eb8bf2c3f65bf7f,0xbf7f3f67bf313ec4,0xbe2f3f04bf4a3f75,0x3f7ebf783f51bf0e,0xbcc9beac3f27bf62,0xbf733f80bf6a3f35,0x3e603e16befc3f46,
0x3e89bf183f58bf7b,0xbf6f3f3ebee63dc9,0xbd973edbbf393f6d,0x3f7cbf5c3f1dbe95,0xbdfbbe793f13bf55,0xbf803f71bf423ef1,0x3ea13d49becf3f35,0x3f7abf7d3f5fbf22,
0xbec43f35bf6d3f80,0x3f6dbf353ec40000,0x3ec4bf353f6dbf80,0xbf6d3f35bec40000,0xbec43f35bf6d3f80,0x3f6dbf353ec40000,0x3ec4bf353f6dbf80,0xbf6d3f35bec40000,
0x3f6dbf353ec48000,0x3ec4bf353f6dbf80,0xbf6d3f35bec48000,0xbec43f35bf6d3f80,0x3f6dbf353ec48000,0x3ec4bf353f6dbf80,0xbf6d3f35bec48000,0xbec43f35bf6d3f80,
0xbf1d3e793e2fbf0e,0xbf393f71bf7f3f62,0x3ee6bd49beb83f35,0x3f58bf7d3f77bf46,0xbf5f3f18be60be48,0xbecf3f3ebf733f7f,0x3f42bedb3cc93ec4,0x3f13bf5c3f7ebf75,
0xbf4a3f78bf7c3f55,0x3f31beacbd973ef1,0x3f65bf803f6fbf35,0xbf093e163e89bf22,0xbefc3f4ebf7a3f7b,0x3f6abf2c3ea13dc9,0x3f27bf673f80bf6d,0xbf513f04bdfbbe95,
0x3f5cbf7f3f71bf35,0xbf2c3e953e16bf0e,0xbf183f62bf803f6d,0x3f67bf223e793e48,0x3f78bf463edb0000,0x3d49bef13f4ebf7b,0xbf7d3f75bf3e3ec4,0x3eac3dc9bf043f55,
0xbf043dc93eacbf35,0xbf3e3f75bf7d3f55,0x3f4ebef13d493ec4,0x3edbbf463f78bf7b,0x3e79bf223f67bf80,0xbf803f62bf183e48,0x3e163e95bf2c3f6d,0x3f71bf7f3f5cbf0e,
0x3f39beacbdfb3f0e,0x3ee6bf4e3f7cbf75,0xbe60be793f27bf6d,0xbf5f3f80bf6a3f22,0xbeb83f3ebf773f7b,0x3f7fbf5c3f09bdc9,0x3f51bf7d3f73bf35,0xbf4a3edb3cc9bef1,
0x3f31bf713f7ebf55,0xbf653f18be2fbe95,0xbf7a3f78bf423ec4,0x3efcbd49becf3f46,0x3f6fbf2c3e893e48,0x3d97bf043f58bf7f,0xbf133e163ea1bf35,0xbf1d3f67bf803f62,
0x3dc9bf0e3f62bf80,0xbf753f7bbf463ec4,0x3f22be48be953f35,0x3ef1bf553f7fbf6d,0xbf7f3f55bef10000,0x3e953e48bf223f6d,0x3f46bf7b3f75bf35,0xbf623f0ebdc9bec4,
0xbf7f3f55bef18000,0x3e953e48bf223f6d,0x3f46bf7b3f75bf35,0xbf623f0ebdc9bec4,0xbdc93f0ebf623f80,0x3f75bf7b3f46bec4,0xbf223e483e95bf35,0xbef13f55bf7f3f6d,
0x3f7cbf713f27be48,0xbf1d3e163eb8bf46,0xbf313e793e89bf35,0xbea13f3ebf7a3f75,0xbf093d493ee6bf55,0xbefc3f5cbf803f62,0xbecf3f4ebf7e3f6d,0x3f7fbf673f13bdc9,
0xbe2fbeac3f42bf7b,0xbf4a3f7dbf6f3f22,0xbf393f78bf773f35,0x3f73bf2c3e603e95,0xbf583f80bf653f0e,0x3f5fbf043cc93ef1,0x3f6abf183dfb3ec4,0xbd97bedb3f51bf7f,
0x3f3ebe95be793f35,0x3e16bf223f71bf7b,0xbf673f7fbf4e3ec4,0x3f5cbef1bd493f0e,0xbf803f62bf040000,0x3f18bdc9bedb3f55,0x3eacbf463f7dbf6d,0xbf783f75bf2c3e48,
0x3f2cbf753f78bf35,0xbf7d3f46beacbe48,0x3edb3dc9bf183f6d,0x3f04bf623f80bf55,0x3d493ef1bf5c3f80,0x3f4ebf7f3f67bf0e,0xbf713f22be16bec4,0x3e793e95bf3e3f7b,
0x3ea13e79bf393f7b,0x3f09bf673f7ebf46,0x3f5fbf803f51bec4,0xbf6f3f18bd97bef1,0xbf273e163ecfbf55,0xbe2f3f2cbf773f75,0xbf1d3f71bf7a3f35,0x3f80bf5c3ee63dc9,
0x3f73bf783f31be48,0xbf583edb3dfbbf22,0xbefcbd493f13bf6d,0xbeb83f4ebf7f3f62,0xbf423f7dbf6a3f0e,0x3f7cbf3e3e893e95,0x3f4abeacbe603f35,0xbcc9bf043f65bf7f,
0x3e483ec4bf553f80,0x3f0ebf6d3f7bbf35,0xbf7b3f6dbf0e0000,0x3f55bec4be483f35,0xbe48bec43f55bf80,0xbf0e3f6dbf7b3f35,0x3f7bbf6d3f0e0000,0xbf553ec43e48bf35,
0x3f7bbf6d3f0e8000,0xbf553ec43e48bf35,0x3e483ec4bf553f80,0x3f0ebf6d3f7bbf35,0xbf7b3f6dbf0e8000,0x3f55bec4be483f35,0xbe48bec43f55bf80,0xbf0e3f6dbf7b3f35,
0xbea13f4ebf803f55,0x3f58bf803f4abe95,0x3f5fbedbbe2f3f35,0xbeb8be793f42bf7f,0xbd97bf043f6abf7b,0xbf133f71bf773f22,0xbf7e3f3ebe60bec4,0x3f31be16bee63f62,
0x3f73bf183cc93f0e,0xbf09bd493f1dbf75,0x3efcbf673f7cbf35,0xbf6f3f78bf273dc9,0xbf7f3f5cbecfbe48,0x3f51beacbe893f46,0xbdfb3f2cbf7a3f6d,0x3f39bf7d3f65bef1,
0xbedb3f62bf7d3f35,0x3f5cbf7f3f3ebe48,0xbf803f46be79bec4,0x3f4ebe95beac3f55,0x3f71bf753f180000,0xbf783f22bd49bf0e,0x3f2cbdc9bf043f6d,0xbe16bef13f67bf7b,
0x3f67bef1be163f35,0xbf04bdc93f2cbf7b,0xbd493f22bf783f6d,0x3f18bf753f71bf0e,0xbeacbe953f4ebf80,0xbe793f46bf803f55,0x3f3ebf7f3f5cbec4,0xbf7d3f62bedbbe48,
0xbe2f3f3ebf7f3f55,0x3f1dbf783f6abef1,0x3f39be16befc3f6d,0xbea1beac3f58bf7f,0x3f7abf673ee63e48,0xbf773f183cc9bf22,0x3eb8bf5c3f7ebf35,0xbf423f80bf513e95,
0x3f7cbf2c3d973f0e,0xbf4a3e793ecfbf62,0x3f31bf7d3f5fbec4,0xbf733f71bf09bdc9,0xbe60bedb3f65bf7b,0xbe893f4ebf803f46,0xbf6f3f043dfbbf35,0x3f27bd49bf133f75,
0xbef1be483f46bf80,0x3dc93f0ebf753f6d,0x3e95bf553f7fbf35,0xbf223f7bbf623ec4,0x3f62bf7b3f220000,0xbf7f3f55be95bec4,0x3f75bf0ebdc93f35,0xbf463e483ef1bf6d,
0xbf623f7bbf228000,0x3f7fbf553e953ec4,0xbf753f0e3dc9bf35,0x3f46be48bef13f6d,0xbef1be483f46bf80,0x3dc93f0ebf753f6d,0x3e95bf553f7fbf35,0xbf223f7bbf623ec4,
0xbf313d493f1dbf7b,0x3ee63e79bf513f7f,0xbf7a3f183d97bf35,0x3f5fbeacbeb83f62,0x3ecfbf673f77bf0e,0xbf273f7dbf583e95,0xbe2fbf043f73bf6d,0xbdfb3f3ebf803f46,
0xbf393f80bf4a3e48,0x3f65bf783f133dc9,0xbe603f4ebf7f3f35,0x3efcbf713f6fbef1,0xbf6a3edb3e89bf55,0x3f42be16bf093f75,0xbf7c3f5cbea1bec4,0x3f7ebf2c3cc93f22,
0xbf7d3f223d49bf35,0x3f71bef1be793f55,0xbf5c3e953edbbf6d,0x3f3ebdc9bf183f7b,0xbf4e3f7fbf2c0000,0x3f67bf753f043e48,0xbf783f62beacbec4,0x3f80bf463e163f0e,
0xbe163f46bf803f35,0x3eacbf623f78bf0e,0xbf043f75bf673ec4,0x3f2cbf7f3f4ebe48,0x3f183dc9bf3e3f80,0xbedbbe953f5cbf7b,0x3e793ef1bf713f6d,0xbd49bf223f7dbf55,
0xbf1d3f7dbf513e48,0x3f31bf803f42bdc9,0xbee63f71bf6a3ec4,0x3f09bf783f5fbe95,0xbe893f5cbf7a3f0e,0x3eb8bf673f73bef1,0xbd973f3ebf803f35,0x3e2fbf4e3f7ebf22,
0x3f4abe16bf133f7b,0xbf393d493f27bf7f,0x3f65beacbecf3f6d,0xbf583e793efcbf75,0x3f77bf04be603f55,0xbf6f3edb3ea1bf62,0x3f7fbf2cbcc93f35,0xbf7c3f183dfbbf46,
0x3f350000bf353f80,0xbf3500003f35bf80,0x3f350000bf353f80,0xbf3500003f35bf80,0x3f350000bf353f80,0xbf3500003f35bf80,0x3f350000bf353f80,0xbf3500003f35bf80,
0xbf353f80bf358000,0x3f35bf803f358000,0xbf353f80bf358000,0x3f35bf803f358000,0xbf353f80bf358000,0x3f35bf803f358000,0xbf353f80bf358000,0x3f35bf803f358000,
0xbe89bf783e603f7b,0xbeb8bf713ea13f75,0xbd97bf803cc93f80,0xbe2fbf7d3dfb3f7f,0xbf1dbf4e3f133f55,0xbf31bf3e3f273f46,0xbee6bf673ecf3f6d,0xbf09bf5c3efc3f62,
0xbf773e793f7abe48,0xbf6f3eac3f73be95,0xbf7f3d493f808000,0xbf7c3e163f7ebdc9,0xbf4a3f183f51bf0e,0xbf393f2c3f42bf22,0xbf653edb3f6abec4,0xbf583f043f5fbef1,
0xbf4ebf223f3e3f35,0xbf67bef13f5c3f0e,0xbf78be953f713ec4,0xbf80bdc93f7d3e48,0xbe16bf7f3d493f80,0xbeacbf753e793f7b,0xbf04bf623edb3f6d,0xbf2cbf463f183f55,
0xbf183f463f2cbf35,0xbedb3f623f04bf55,0xbe793f753eacbf6d,0xbd493f7f3e16bf7b,0xbf7d3dc93f808000,0xbf713e953f78be48,0xbf5c3ef13f67bec4,0xbf3e3f223f4ebf0e,
0xbf6a3eac3f77be48,0xbf423f183f58bef1,0xbf7cbe793f733ec4,0xbf7e3d493f803dc9,0xbf39bf3e3f1d3f55,0xbf65bf043f513f22,0xbe60bf7d3d973f80,0xbefcbf673eb83f75,
0x3ecf3f71be89bf7b,0x3f273f4ebf09bf62,0xbe2f3f783ea1bf6d,0x3dfb3f803cc9bf7f,0xbf313f2c3f4abf0e,0xbee63f5c3f13bf46,0xbf7a3e163f7f8000,0xbf5f3edb3f6fbe95,
0xbe95bf7b3dc93f80,0xbf22bf553ef13f6d,0xbf62bf0e3f463f35,0xbf7fbe483f753ec4,0xbf753e483f7f0000,0xbf463f0e3f62bec4,0xbef13f553f22bf35,0xbdc93f7b3e95bf6d,
0xbf753e483f7f8000,0xbf463f0e3f62bec4,0xbef13f553f22bf35,0xbdc93f7b3e95bf6d,0x3e953f7bbdc9bf80,0x3f223f55bef1bf6d,0x3f623f0ebf46bf35,0x3f7f3e48bf75bec4,
0xbf7abeac3f653f0e,0xbf773e163f803dc9,0xbeb8bf783dfb3f80,0xbf42bf3e3f133f62,0x3e2f3f803d97bf7b,0x3f1d3f5cbecfbf75,0xbf393f183f5fbec4,0xbea13f673f09bf46,
0xbe603f713ee6bf55,0x3e893f7dbcc9bf7f,0xbf6f3e793f7e8000,0xbf273f2c3f51bef1,0x3f7cbd49bf7fbe48,0x3f4abf04bf6a3e95,0x3f313f4ebefcbf6d,0x3f733edbbf58bf22,
0xbeac3f623f18bf35,0x3e793f7f3d49bf7b,0x3f3e3f46bf04bf6d,0x3f7d3e95bf67bf0e,0xbedbbf753e163f80,0xbf5cbf223f2c3f55,0xbf80bdc93f783ec4,0xbf4e3ef13f71be48,
0x3f713ef1bf4ebf35,0x3f78bdc9bf80be48,0x3f2cbf22bf5c3ec4,0x3e16bf75bedb3f55,0xbf673e953f7d8000,0xbf043f463f3ebf0e,0x3d493f7f3e79bf6d,0x3f183f62beacbf7b,
0x3f7f3e79bf6abf0e,0x3f51bedbbf773dc9,0x3dfb3f803e60bf6d,0x3f393f4ebee6bf75,0xbf733e163f803e48,0xbf093f3e3f4abef1,0xbefcbf713e2f3f80,0xbf6fbf043f423f46,
0x3d97bf78becf3f55,0xbf13bf673e893f7f,0x3f7e3d49bf7abec4,0x3f31bf18bf653e95,0x3ea13f7d3cc9bf7b,0x3f583f2cbf1dbf62,0xbf5f3eac3f7c8000,0xbeb83f5c3f27bf22,
0xbf0ebf6d3e483f80,0xbf7bbec43f553f35,0xbf553ec43f7b0000,0xbe483f6d3f0ebf35,0x3f0e3f6dbe48bf80,0x3f7b3ec4bf55bf35,0x3f55bec4bf7b0000,0x3e48bf6dbf0e3f35,
0xbf553ec43f7b8000,0xbe483f6d3f0ebf35,0x3f0e3f6dbe48bf80,0x3f7b3ec4bf55bf35,0x3f55bec4bf7b8000,0x3e48bf6dbf0e3f35,0xbf0ebf6d3e483f80,0xbf7bbec43f553f35,
0xbf273f183f6abe48,0x3e2f3f803e89bf62,0xbf1dbf673e603f80,0xbf80be793f653f22,0x3ea1bf5cbf313f0e,0xbf09bf713dfb3f7f,0x3f5f3f2cbf13bf6d,0x3f6fbe16bf7fbe95,
0x3f423f4ebecfbf7b,0x3f7c3d49bf77bef1,0xbf4a3edb3f7a8000,0xbcc93f783ee6bf46,0xbf73bf043f393f55,0xbf583eac3f7e3dc9,0x3efcbf3ebf513ec4,0xbeb8bf7dbd973f75,
0x3f803e95bf5cbf35,0x3f18bf22bf673e48,0xbeacbf7fbe163f6d,0xbf78bef13f3e3f55,0xbf2cbf623e793f80,0xbf7dbdc93f713f0e,0xbedb3f463f4ebec4,0x3f043f75bd49bf7b,
0x3d49bf75bf043f35,0xbf4ebf463edb3f7b,0xbf713dc93f7d3ec4,0xbe793f623f2cbf0e,0xbf3e3ef13f788000,0x3e163f7f3eacbf55,0x3f673f22bf18bf6d,0x3f5cbe95bf80be48,
0xbf58bf3e3ee63f7b,0xbf5f3e793f803e95,0x3f6abe16bf7ebec4,0x3d97bf71bf133f22,0xbe2f3f673f27bf0e,0x3f4a3f4ebeb8bf7f,0xbf39bf5c3e893f80,0xbf733d493f7a3ef1,
0xbf093f2c3f65be48,0x3efc3f783cc9bf75,0xbecfbf7dbdfb3f6d,0xbf7fbeac3f513f46,0x3f7c3edbbf42bf55,0x3f1dbf18bf6f3dc9,0xbf313f043f778000,0x3ea13f803e60bf62,
0xbf46bf553e953f80,0xbf623e483f7f3ec4,0x3dc93f7b3ef1bf35,0x3f753f0ebf22bf6d,0x3f22bf0ebf750000,0xbef1bf7bbdc93f6d,0xbf7fbe483f623f35,0xbe953f553f46bec4,
0xbf223f0e3f758000,0x3ef13f7b3dc9bf6d,0x3f7f3e48bf62bf35,0x3e95bf55bf463ec4,0xbf46bf553e953f80,0xbf623e483f7f3ec4,0x3dc93f7b3ef1bf35,0x3f753f0ebf22bf6d,
0x3eb83f803e89bf55,0x3f7f3e79bf58bf46,0xbf51bf4e3ea13f80,0xbf4a3eac3f803e95,0xbf393edb3f7e3e48,0x3ee63f7d3e2fbf62,0x3e60bf5cbf423ec4,0xbf5fbf3e3ecf3f7f,
0x3f6fbd49bf77bf0e,0xbd97bf78bf093f22,0xbf133f183f738000,0x3f1d3f71bcc9bf75,0x3f313f67bdfbbf7b,0x3f65be16bf7cbef1,0xbf7abf043f273f6d,0xbefc3f2c3f6abdc9,
0xbe79bf7fbedb3f35,0xbf80be953f4e3f55,0xbe163f623f3ebec4,0x3f713f22bf04bf7b,0xbf5cbf463eac3f80,0xbf2c3ef13f7d3e48,0x3f183f753d49bf6d,0x3f67bdc9bf78bf0e,
0xbf78bdc93f673f35,0x3d493f753f18bf0e,0x3f7d3ef1bf2cbf6d,0x3eacbf46bf5c3e48,0xbf043f223f718000,0x3f3e3f62be16bf7b,0x3f4ebe95bf80bec4,0xbedbbf7fbe793f55,
0x3efc3f7d3e60bf55,0x3f6abd49bf73bf22,0xbf27bf71bcc93f6d,0xbf513e793f7e3ef1,0x3f4a3f5cbe2fbf7b,0x3f31bedbbf7fbe95,0xbf65bf3e3eb83f80,0xbf093f183f773dc9,
0x3f5fbe16bf7abf0e,0xbecfbf80bea13f46,0xbf423eac3f803ec4,0x3f133f783dfbbf62,0x3f1dbf04bf7cbe48,0xbf39bf673d973f75,0xbee63f2c3f6f8000,0x3f583f4ebe89bf7f,
0xbf6dbf353ec43f80,0xbec43f353f6d0000,0x3f6d3f35bec4bf80,0x3ec4bf35bf6d0000,0xbf6dbf353ec43f80,0xbec43f353f6d0000,0x3f6d3f35bec4bf80,0x3ec4bf35bf6d0000,
0xbec43f353f6d8000,0x3f6d3f35bec4bf80,0x3ec4bf35bf6d8000,0xbf6dbf353ec43f80,0xbec43f353f6d8000,0x3f6d3f35bec4bf80,0x3ec4bf35bf6d8000,0xbf6dbf353ec43f80,
0x3f7e3f04bf13bf7b,0x3cc9bf67bf423e95,0xbf73bf2c3ecf3f80,0xbe603f4e3f5fbdc9,0x3f773e16bf58bf55,0xbeb8bf80bee63f22,0xbf7fbeac3f393f6d,0x3e2f3f783f1dbef1,
0x3dfbbf5cbf513e48,0xbf80bedb3f273f75,0xbea13f3e3f6a8000,0x3f7a3f18befcbf7f,0xbe89bf7dbf093f0e,0xbf6fbd493f653f46,0x3d973f713f31bec4,0x3f7c3e79bf4abf62,
0xbf5c3dc93f713f35,0x3f2c3f753e16bf55,0x3f18bef1bf80bec4,0xbf67bf463e793f7b,0xbf78bf223edb3f80,0xbd493f623f4ebe48,0x3f7d3e95bf3ebf6d,0xbeacbf7fbf043f0e,
0x3f043f7f3eacbf35,0x3f3ebe95bf7dbf0e,0xbf4ebf623d493f6d,0xbedb3f223f783e48,0xbe793f463f678000,0x3f803ef1bf18bf7b,0xbe16bf75bf2c3ec4,0xbf71bdc93f5c3f55,
0xbcc9bf67bf4a3e48,0xbf73be163f513f62,0xbf093f043f7f3ec4,0x3f773f2cbeb8bf7f,0x3f6a3d49bf5fbf55,0xbf27bf78be603f46,0xbf7cbf183ee63f80,0x3dfb3f713f39be95,
0xbf80bedb3f1d3f7b,0x3ea13f7d3f13bef1,0x3f583f5cbd97bf6d,0x3e89bf3ebf6fbdc9,0xbecfbf80befc3f0e,0xbf423e793f7a3f22,0xbe2f3f4e3f658000,0x3f7e3eacbf31bf75,
0xbf7fbf0e3ef13f80,0x3e953f7b3f22bec4,0x3f46be48bf75bf35,0xbf62bf553dc93f6d,0xbdc93f553f620000,0x3f753e48bf46bf6d,0xbf22bf7bbe953f35,0xbef13f0e3f7f3ec4,
0xbdc93f553f628000,0x3f753e48bf46bf6d,0xbf22bf7bbe953f35,0xbef13f0e3f7f3ec4,0x3f7f3f0ebef1bf80,0xbe95bf7bbf223ec4,0xbf463e483f753f35,0x3f623f55bdc9bf6d,
0x3f13bedbbf7fbf0e,0xbf7ebf183ecf3f7f,0xbf80bf043efc3f80,0x3ee63f803f09bef1,0xbf7abf2c3ea13f7b,0x3e893f783f31be95,0x3eb83f7d3f1dbec4,0x3f27beacbf7cbf22,
0xbf51bf67bd973f55,0xbdfb3f4e3f6a3dc9,0xbcc93f5c3f5f8000,0x3f653d49bf58bf62,0xbe603f3e3f733e48,0x3f773e79bf39bf75,0x3f6f3e16bf4abf6d,0xbf42bf71be2f3f46,
0x3f3e3f753e79bf35,0x3e16bf46bf71be48,0xbf67bdc93f4e3f6d,0x3f5c3f623d49bf55,0xbf80bef13f043f80,0x3f183f7f3edbbf0e,0x3eacbf22bf7dbec4,0xbf78be953f2c3f7b,
0x3f2cbe95bf78bf35,0xbf7dbf223eac3f7b,0x3edb3f7f3f18bec4,0x3f04bef1bf80bf0e,0x3d493f623f5c8000,0x3f4ebdc9bf67bf55,0xbf71bf463e163f6d,0x3e793f753f3ebe48,
0xbee63f043f803f0e,0x3f7a3eacbf1dbf7f,0x3f773f3ebe2fbf6d,0xbecfbf7dbf273e95,0x3d97bf4ebf6fbe48,0xbf513d493f5f3f62,0xbf7ebedb3f093f80,0x3f393f783ea1bf22,
0x3f653f5c3cc9bf55,0xbe60bf71bf4a3dc9,0x3e89bf2cbf7cbec4,0xbf6abe163f423f75,0xbf7fbf183eb83f7b,0x3f133f803efcbef1,0x3dfb3f673f588000,0x3f31be79bf73bf46,
0xbf7bbec43f0e3f80,0x3f553f6d3e48bf35,0xbe48bf6dbf550000,0xbf0e3ec43f7b3f35,0x3f7b3ec4bf0ebf80,0xbf55bf6dbe483f35,0x3e483f6d3f550000,0x3f0ebec4bf7bbf35,
0x3e483f6d3f558000,0x3f0ebec4bf7bbf35,0xbf7bbec43f0e3f80,0x3f553f6d3e48bf35,0xbe48bf6dbf558000,0xbf0e3ec43f7b3f35,0x3f7b3ec4bf0ebf80,0xbf55bf6dbe483f35,
0xbee6bf7dbf313e48,0xbe603f2c3f7e3ef1,0xbf77beac3f133f80,0x3f6a3f5c3d97bf46,0x3f423f783eb8bf0e,0xbe2fbf67bf5fbdc9,0x3f4abd49bf58bf6d,0xbf80bf183ea13f75,
0xbf65be163f393f7b,0x3f7a3f3ebdfbbf62,0x3e893f713f518000,0x3ecfbf04bf7fbf22,0x3f27be79bf6fbf55,0xbf7cbedb3efc3f7f,0xbf1dbf80bf093ec4,0xbcc93f4e3f733e95,
0x3edbbef1bf7dbf35,0xbf5cbdc93f3e3f7b,0x3f803f22be79bf6d,0xbf4ebf75beac3f0e,0xbf71be953f183f80,0x3f783f46bd49bf55,0xbf2cbf7fbf043ec4,0x3e163f623f673e48,
0xbf67bf62be163f35,0x3f043f7f3f2cbe48,0x3d49bf46bf78bec4,0xbf183e953f713f55,0x3eac3f753f4e8000,0x3e79bf22bf80bf0e,0xbf3e3dc93f5c3f6d,0x3f7d3ef1bedbbf7b,
0x3f513d49bf42bf7b,0xbf7ebf043eb83f75,0xbcc9bf4ebf77bec4,0xbee63edb3f7a3f46,0xbf58bf71bea13f0e,0x3efc3f7d3f39bdc9,0xbf6abe793f1d3f80,0x3f7f3f2cbe2fbf62,
0xbf13bf80bf273e48,0x3dfb3f5c3f6f3e95,0xbf80bf183e893f6d,0x3f653f673e60bf22,0xbf093eac3f733f55,0x3f5f3e16bf31bf7f,0x3ecf3f783f4a8000,0x3d97bf3ebf7cbef1,
0xbf62be483f223f80,0x3f7f3f0ebe95bf6d,0xbf75bf55bdc93f35,0x3f463f7b3ef1bec4,0xbef1bf7bbf460000,0x3dc93f553f753ec4,0x3e95bf0ebf7fbf35,0xbf223e483f623f6d,
0x3ef13f7b3f468000,0xbdc9bf55bf75bec4,0xbe953f0e3f7f3f35,0x3f22be48bf62bf6d,0xbf62be483f223f80,0x3f7f3f0ebe95bf6d,0xbf75bf55bdc93f35,0x3f463f7b3ef1bec4,
0xbf80bf2c3dfb3f55,0x3f733f5c3e2fbf22,0xbf58be163f273f80,0x3f773edbbecfbf75,0xbeb8bf71bf5fbe48,0x3d973f4e3f7a3ef1,0xbf51bf78bee63ec4,0x3f1d3f803f31bdc9,
0xbcc93f3e3f7e3f0e,0x3ea1bf04bf7cbf46,0x3f093f7d3f428000,0xbe89bf67bf6abe95,0xbf6fbeac3efc3f7b,0x3f7f3f18be60bf62,0xbf133e793f653f6d,0x3f4a3d49bf39bf7f,
0xbf7dbf46bd493f35,0x3f713f623e79bf0e,0xbf5cbf75bedb3ec4,0x3f3e3f7f3f18be48,0xbf4ebdc93f2c3f80,0x3f673e95bf04bf7b,0xbf78bef13eac3f6d,0x3f803f22be16bf55,
0xbe163f223f803f35,0x3eacbef1bf78bf55,0xbf043e953f673f6d,0x3f2cbdc9bf4ebf7b,0x3f183f7f3f3e8000,0xbedbbf75bf5cbe48,0x3e793f623f713ec4,0xbd49bf46bf7dbf0e,
0xbf7ebf183e2f3f55,0x3f803f2cbd97bf46,0xbf73bedb3eb83f6d,0x3f7a3f04be89bf62,0xbf5fbe793f093f7b,0x3f6a3eacbee6bf75,0xbf42bd493f313f80,0x3f513e16bf1dbf7f,
0x3dfb3f4e3f7c3f0e,0xbcc9bf3ebf7fbf22,0x3ea13f673f6f3ec4,0xbe60bf5cbf77bef1,0x3efc3f783f583e48,0xbecfbf71bf65be95,0x3f273f803f398000,0xbf13bf7dbf4abdc9,
0x3f350000bf353f80,0xbf3500003f35bf80,0x3f350000bf353f80,0xbf3500003f35bf80,0x3f350000bf353f80,0xbf3500003f35bf80,0x3f350000bf353f80,0xbf3500003f35bf80,
0xbf353f80bf358000,0x3f35bf803f358000,0xbf353f80bf358000,0x3f35bf803f358000,0xbf353f80bf358000,0x3f35bf803f358000,0xbf353f80bf358000,0x3f35bf803f358000,
0xbf5fbf043f583f0e,0xbf6abedb3f653ef1,0xbf42bf2c3f393f35,0xbf51bf183f4a3f22,0xbf7ebe163f7c3e48,0xbf80bd493f7f3dc9,0xbf73beac3f6f3ec4,0xbf7abe793f773e95,
0xbefc3f5c3f09bf55,0xbecf3f673ee6bf62,0xbf273f3e3f31bf35,0xbf133f4e3f1dbf46,0xbdfb3f7d3e2fbf7b,0xbcc93f803d97bf7f,0xbea13f713eb8bf6d,0xbe603f783e89bf75,
0xbf183f463f2cbf35,0xbedb3f623f04bf55,0xbe793f753eacbf6d,0xbd493f7f3e16bf7b,0xbf7d3dc93f800000,0xbf713e953f78be48,0xbf5c3ef13f67bec4,0xbf3e3f223f4ebf0e,
0x3f4e3f22bf3ebf35,0x3f673ef1bf5cbf0e,0x3f783e95bf71bec4,0x3f803dc9bf7dbe48,0x3e163f7fbd49bf80,0x3eac3f75be79bf7b,0x3f043f62bedbbf6d,0x3f2c3f46bf18bf55,
0x3f6f3edbbf5fbf0e,0x3f7f3e16bf7abe95,0x3f133f5cbee6bf6d,0x3f4a3f2cbf31bf46,0x3cc93f803dfbbf7b,0x3ea13f78be2fbf7f,0xbf093f4e3f27bf35,0xbe893f713ecfbf62,
0x3eb8bf67befc3f55,0x3d97bf7dbe603f75,0x3f51bf04bf653ec4,0x3f1dbf3ebf393f22,0x3f803d49bf7ebe48,0x3f73be79bf7c3dc9,0x3f583f18bf42bf35,0x3f773eacbf6abef1,
0x3e953f7bbdc9bf80,0x3f223f55bef1bf6d,0x3f623f0ebf46bf35,0x3f7f3e48bf75bec4,0x3f75be48bf7f0000,0x3f46bf0ebf623ec4,0x3ef1bf55bf223f35,0x3dc9bf7bbe953f6d,
0x3f75be48bf7f8000,0x3f46bf0ebf623ec4,0x3ef1bf55bf223f35,0x3dc9bf7bbe953f6d,0xbe95bf7b3dc93f80,0xbf22bf553ef13f6d,0xbf62bf0e3f463f35,0xbf7fbe483f753ec4,
0x3f58bedbbf733e48,0x3efcbf4ebf313f22,0x3f6a3f04bf4abf35,0x3f7f3d49bf7cbe95,0xbf51bf2c3f273f55,0xbf7ebe793f6f3ef1,0x3cc9bf7dbe893f6d,0xbee6bf713e603f7f,
0xbf09bf673ea13f7b,0xbf5fbf183f393f46,0x3ecfbf5cbf1d3f35,0xbd97bf80be2f3f75,0xbf133f3e3f42bf0e,0xbdfb3f783eb8bf62,0xbf80be163f773ec4,0xbf653eac3f7abdc9,
0xbf71bef13f4e3f35,0xbf783dc93f803e48,0xbf2c3f223f5cbec4,0xbe163f753edbbf55,0x3f67be95bf7d0000,0x3f04bf46bf3e3f0e,0xbd49bf7fbe793f6d,0xbf18bf623eac3f7b,
0xbeac3f623f18bf35,0x3e793f7f3d49bf7b,0x3f3e3f46bf04bf6d,0x3f7d3e95bf67bf0e,0xbedbbf753e163f80,0xbf5cbf223f2c3f55,0xbf80bdc93f783ec4,0xbf4e3ef13f71be48,
0x3f273f5cbeb8bf7b,0x3f7c3eacbf5fbf22,0xbf1d3f2c3f58bec4,0x3cc93f7d3ea1bf62,0xbf65bf183f313f55,0xbf7a3d493f7e3e95,0x3e89bf67bf133f35,0xbecfbf783d973f7f,
0x3f42bf04bf6f3e48,0x3e2fbf71befc3f46,0x3f4a3f3ebf09bf6d,0x3f803e16bf73bef1,0xbee63f4e3f39bf0e,0x3e603f803dfbbf75,0xbf77bedb3f513f35,0xbf6a3e793f7f3dc9,
0xbf0ebf6d3e483f80,0xbf7bbec43f553f35,0xbf553ec43f7b0000,0xbe483f6d3f0ebf35,0x3f0e3f6dbe48bf80,0x3f7b3ec4bf55bf35,0x3f55bec4bf7b0000,0x3e48bf6dbf0e3f35,
0xbf553ec43f7b8000,0xbe483f6d3f0ebf35,0x3f0e3f6dbe48bf80,0x3f7b3ec4bf55bf35,0x3f55bec4bf7b8000,0x3e48bf6dbf0e3f35,0xbf0ebf6d3e483f80,0xbf7bbec43f553f35,
0x3d973f7d3eb8bf55,0x3f513f3ebefcbf75,0xbf7ebeac3f583f35,0xbf393f043f73bdc9,0xbee6bf783cc93f7b,0xbf7abedb3f4a3f46,0x3f77bd49bf7cbec4,0x3ecfbf4ebf423ef1,
0x3f7f3e16bf6fbf0e,0x3f13bf2cbf5f3e95,0xbdfb3f713f09bf35,0x3f313f5cbea1bf7f,0xbf653e793f803e48,0xbe603f673f1dbf22,0xbe89bf80be2f3f6d,0xbf6abf183f273f62,
0x3d49bf75bf043f35,0xbf4ebf463edb3f7b,0xbf713dc93f7d3ec4,0xbe793f623f2cbf0e,0xbf3e3ef13f780000,0x3e163f7f3eacbf55,0x3f673f22bf18bf6d,0x3f5cbe95bf80be48,
0xbf80be953f5c3f35,0xbf183f223f67be48,0x3eac3f7f3e16bf6d,0x3f783ef1bf3ebf55,0x3f2c3f62be79bf80,0x3f7d3dc9bf71bf0e,0x3edbbf46bf4e3ec4,0xbf04bf753d493f7b,
0x3e603f803ea1bf55,0x3f773f04bf31bf62,0xbf6fbf183f1d3f6d,0xbf423edb3f7c3dc9,0x3f51beacbf7fbe48,0xbdfbbf7dbecf3f46,0x3cc93f783efcbf35,0x3f653f2cbf09bf75,
0x3f7a3d49bf73bf0e,0x3e89bf5cbf393ef1,0xbeb83f4e3f4abec4,0x3f273f67be2fbf7f,0xbf13bf713d973f7b,0xbf7ebe163f6a3f22,0x3f803e79bf5fbf35,0x3ee6bf3ebf583e95,
0x3f463f55be95bf80,0x3f62be48bf7fbec4,0xbdc9bf7bbef13f35,0xbf75bf0e3f223f6d,0xbf223f0e3f750000,0x3ef13f7b3dc9bf6d,0x3f7f3e48bf62bf35,0x3e95bf55bf463ec4,
0x3f22bf0ebf758000,0xbef1bf7bbdc93f6d,0xbf7fbe483f623f35,0xbe953f553f46bec4,0x3f463f55be95bf80,0x3f62be48bf7fbec4,0xbdc9bf7bbef13f35,0xbf75bf0e3f223f6d,
0xbf6abf2c3efc3f7b,0xbf273f043f7a3dc9,0x3f7c3e16bf65bf35,0x3dfbbf67bf313ef1,0x3cc9bf71bf1d3f0e,0xbf73bf183f133f75,0x3f093f783d97bf6d,0x3f773d49bf6fbf22,
0xbecf3f3e3f5fbe48,0x3f423f5cbe60bf7f,0xbe2fbf7dbee63f35,0xbf7ebedb3f393f62,0xbf80beac3f4a3f55,0xbea13f4e3f51be95,0x3f58be79bf7fbec4,0xbe89bf80beb83f46,
0x3f783dc9bf67bf35,0xbd49bf75bf183f0e,0xbf7dbef13f2c3f6d,0xbeac3f463f5cbe48,0x3f04bf22bf710000,0xbf3ebf623e163f7b,0xbf4e3e953f803ec4,0x3edb3f7f3e79bf55,
0xbe79bf7fbedb3f35,0xbf80be953f4e3f55,0xbe163f623f3ebec4,0x3f713f22bf04bf7b,0xbf5cbf463eac3f80,0xbf2c3ef13f7d3e48,0x3f183f753d49bf6d,0x3f67bdc9bf78bf0e,
0xbe893f4e3f58be48,0x3f6f3f2cbee6bf7f,0x3d97bf67bf393ec4,0xbf7cbf043f1d3f75,0x3dfb3f783f13bf0e,0x3f803eacbf42bf62,0xbea1bf80becf3f35,0xbf7abe163f5f3f46,
0x3f773f18bf09bf7b,0x3eb8bf3ebf653dc9,0xbf7fbedb3f313f6d,0xbe2f3f5c3f4abe95,0x3f7e3e79bf51bf55,0xbcc9bf71bf273ef1,0xbf73bd493f6a3f35,0x3e603f7d3efcbf22,
0xbf6dbf353ec43f80,0xbec43f353f6d0000,0x3f6d3f35bec4bf80,0x3ec4bf35bf6d0000,0xbf6dbf353ec43f80,0xbec43f353f6d0000,0x3f6d3f35bec4bf80,0x3ec4bf35bf6d0000,
0xbec43f353f6d8000,0x3f6d3f35bec4bf80,0x3ec4bf35bf6d8000,0xbf6dbf353ec43f80,0xbec43f353f6d8000,0x3f6d3f35bec4bf80,0x3ec4bf35bf6d8000,0xbf6dbf353ec43f80,
0x3f4abe79bf7cbf0e,0xbf31bf71bd973f62,0xbf653d493f6f3f35,0x3f093f7d3e89bf46,0x3efcbf18bf7abe48,0xbf6abf3e3ea13f7f,0xbf273edb3f803ec4,0x3f513f5cbdfbbf75,
0xbf1dbf78be2f3f55,0xbf393eac3f7f3ef1,0x3ee63f803eb8bf35,0x3f58be16bf77bf22,0xbf5fbf4e3e603f7b,0xbecf3f2c3f733dc9,0x3f423f67bcc9bf6d,0x3f13bf04bf7ebe95,
0x3f043f7f3eacbf35,0x3f3ebe95bf7dbf0e,0xbf4ebf623d493f6d,0xbedb3f223f783e48,0xbe793f463f670000,0x3f803ef1bf18bf7b,0xbe16bf75bf2c3ec4,0xbf71bdc93f5c3f55,
0x3f5cbdc9bf71bf35,0xbf2cbf75be163f55,0xbf183ef13f803ec4,0x3f673f46be79bf7b,0x3f783f22bedbbf80,0x3d49bf62bf4e3e48,0xbf7dbe953f3e3f6d,0x3eac3f7f3f04bf0e,
0xbf313eac3f7e3f0e,0x3f653f4ebe2fbf75,0x3f7a3e79bf42bf6d,0xbefcbf80becf3f22,0xbf6fbf3e3e893f7b,0xbd973f5c3f58bdc9,0x3f133f7d3ea1bf35,0x3f1dbedbbf80bef1,
0x3f393f713dfbbf55,0x3ee6bf18bf7cbe95,0xbe60bf78bf273ec4,0xbf5f3d493f6a3f46,0xbeb83f2c3f773e48,0x3f7f3f04bf09bf7f,0x3f51be16bf73bf35,0xbf4abf67bcc93f62,
0x3f7f3f0ebef1bf80,0xbe95bf7bbf223ec4,0xbf463e483f753f35,0x3f623f55bdc9bf6d,0x3dc9bf55bf620000,0xbf75be483f463f6d,0x3f223f7b3e95bf35,0x3ef1bf0ebf7fbec4,
0x3dc9bf55bf628000,0xbf75be483f463f6d,0x3f223f7b3e95bf35,0x3ef1bf0ebf7fbec4,0xbf7fbf0e3ef13f80,0x3e953f7b3f22bec4,0x3f46be48bf75bf35,0xbf62bf553dc93f6d,
0x3e2f3f713f42be48,0x3f4abe16bf6fbf46,0x3f39be79bf77bf35,0xbf73bf3e3e603f75,0x3f58bd49bf65bf55,0xbf5fbf5c3cc93f62,0xbf6abf4e3dfb3f6d,0x3d973f673f51bdc9,
0x3f7c3eacbf27bf7b,0xbf1dbf7dbeb83f22,0xbf31bf78be893f35,0xbea13f2c3f7a3e95,0xbf09bf80bee63f0e,0xbefc3f043f803ef1,0xbecf3f183f7e3ec4,0x3f7f3edbbf13bf7f,
0xbf2c3e953f783f35,0x3f7d3f22beacbf7b,0xbedbbf7fbf183ec4,0xbf043ef13f803f0e,0xbd49bf62bf5c0000,0xbf4e3dc93f673f55,0x3f713f46be16bf6d,0xbe79bf75bf3e3e48,
0x3f3e3f753e79bf35,0x3e16bf46bf71be48,0xbf67bdc93f4e3f6d,0x3f5c3f623d49bf55,0xbf80bef13f043f80,0x3f183f7f3edbbf0e,0x3eacbf22bf7dbec4,0xbf78be953f2c3f7b,
0xbf73be793f313f7b,0x3f583f673dfbbf46,0x3efc3f803f13bec4,0x3eb8bf18bf7fbef1,0x3f42be16bf6abf55,0xbf7cbf2c3e893f75,0xbf4abf71be603f35,0x3cc93f5c3f653dc9,
0x3ea13f783f39be48,0x3f09bedbbf7ebf22,0x3f5f3d49bf51bf6d,0xbf6fbf4e3d973f62,0xbf27bf7dbecf3f0e,0xbe2f3f3e3f773e95,0xbf1d3eac3f7a3f35,0x3f803f04bee6bf7f,
0xbf7bbec43f0e3f80,0x3f553f6d3e48bf35,0xbe48bf6dbf550000,0xbf0e3ec43f7b3f35,0x3f7b3ec4bf0ebf80,0xbf55bf6dbe483f35,0x3e483f6d3f550000,0x3f0ebec4bf7bbf35,
0x3e483f6d3f558000,0x3f0ebec4bf7bbf35,0xbf7bbec43f0e3f80,0x3f553f6d3e48bf35,0xbe48bf6dbf558000,0xbf0e3ec43f7b3f35,0x3f7b3ec4bf0ebf80,0xbf55bf6dbe483f35,
0xbf73bf4e3cc93f55,0x3f093f803f1dbe95,0xbefc3edb3f7c3f35,0x3f6f3e79bf27bf7f,0x3f7f3f04becfbf7b,0xbf51bf71be893f22,0x3dfbbf3ebf7abec4,0xbf393e163f653f62,
0xbea13f183f803f0e,0x3f583d49bf4abf75,0x3f5f3f673e2fbf35,0xbeb8bf78bf423dc9,0xbd97bf5cbf6abe48,0xbf133eac3f773f46,0xbf7ebf2c3e603f6d,0x3f313f7d3ee6bef1,
0xbf67bf62be163f35,0x3f043f7f3f2cbe48,0x3d49bf46bf78bec4,0xbf183e953f713f55,0x3eac3f753f4e0000,0x3e79bf22bf80bf0e,0xbf3e3dc93f5c3f6d,0x3f7d3ef1bedbbf7b,
0xbedb3ef13f7d3f35,0x3f5c3dc9bf3ebf7b,0xbf80bf223e793f6d,0x3f4e3f753eacbf0e,0x3f713e95bf18bf80,0xbf78bf463d493f55,0x3f2c3f7f3f04bec4,0xbe16bf62bf67be48,
0xbf7cbf3e3d973f55,0x3f4a3f783ecfbef1,0xbf313e163f5f3f6d,0x3f733eacbf09bf7f,0x3e603f673f653e48,0x3e89bf18bf80bf22,0x3f6f3f5c3dfbbf35,0xbf27bf80bf133e95,
0xbe2f3f2c3f7f3f0e,0x3f1dbe79bf6abf62,0x3f393f7d3efcbec4,0xbea1bf71bf58bdc9,0x3f7a3edbbee6bf7b,0xbf77bf4ebcc93f46,0x3eb8bf04bf7ebf35,0xbf423d493f513f75,
0x3f623e48bf22bf80,0xbf7fbf0e3e953f6d,0x3f753f553dc9bf35,0xbf46bf7bbef13ec4,0x3ef13f7b3f460000,0xbdc9bf55bf75bec4,0xbe953f0e3f7f3f35,0x3f22be48bf62bf6d,
0xbef1bf7bbf468000,0x3dc93f553f753ec4,0x3e95bf0ebf7fbf35,0xbf223e483f623f6d,0x3f623e48bf22bf80,0xbf7fbf0e3e953f6d,0x3f753f553dc9bf35,0xbf46bf7bbef13ec4,
0x3f39bd49bf4abf7b,0xbf65be793f133f7f,0x3e60bf18bf7fbf35,0xbefc3eac3f6f3f62,0x3f6a3f673e89bf0e,0xbf42bf7dbf093e95,0x3f7c3f04bea1bf6d,0xbf7ebf3e3cc93f46,
0xbf31bf80bf1d3e48,0x3ee63f783f513dc9,0xbf7abf4ebd973f35,0x3f5f3f713eb8bef1,0x3ecfbedbbf77bf55,0xbf273e163f583f75,0xbe2fbf5cbf73bec4,0xbdfb3f2c3f803f22,
0x3e16bf22bf80bf35,0xbeac3ef13f783f55,0x3f04be95bf67bf6d,0xbf2c3dc93f4e3f7b,0xbf18bf7fbf3e0000,0x3edb3f753f5c3e48,0xbe79bf62bf71bec4,0x3d493f463f7d3f0e,
0xbf7dbf46bd493f35,0x3f713f623e79bf0e,0xbf5cbf75bedb3ec4,0x3f3e3f7f3f18be48,0xbf4ebdc93f2c3f80,0x3f673e95bf04bf7b,0xbf78bef13eac3f6d,0x3f803f22be16bf55,
0xbf4abf7dbf133e48,0x3f393f803f27bdc9,0xbf65bf71becf3ec4,0x3f583f783efcbe95,0xbf77bf5cbe603f0e,0x3f6f3f673ea1bef1,0xbf7fbf3ebcc93f35,0x3f7c3f4e3dfbbf22,
0xbf1d3e163f513f7b,0x3f31bd49bf42bf7f,0xbee63eac3f6a3f6d,0x3f09be79bf5fbf75,0xbe893f043f7a3f55,0x3eb8bedbbf73bf62,0xbd973f2c3f803f35,0x3e2fbf18bf7ebf46,
0x3f003f003f003f00,0x3f003f003f003f00,0x3f003f003f003f00,0x3f003f003f003f00,0x3f003f003f003f00,0x3f003f003f003f00,0x3f003f003f003f00,0x3f003f003f003f00,
0xbf003f00bf003f00,0xbf003f00bf003f00,0xbf003f00bf003f00,0xbf003f00bf003f00,0xbf003f00bf003f00,0xbf003f00bf003f00,0xbf003f00bf003f00,0xbf003f00bf003f00,
0xbe89be79be60be48,0xbeb8beacbea1be95,0xbd97bd49bcc90000,0xbe2fbe16bdfbbdc9,0xbf1dbf18bf13bf0e,0xbf31bf2cbf27bf22,0xbee6bedbbecfbec4,0xbf09bf04befcbef1,
0xbf77bf78bf7abf7b,0xbf6fbf71bf73bf75,0xbf7fbf80bf80bf80,0xbf7cbf7dbf7ebf7f,0xbf4abf4ebf51bf55,0xbf39bf3ebf42bf46,0xbf65bf67bf6abf6d,0xbf58bf5cbf5fbf62,
0xbf18bf22bf2cbf35,0xbedbbef1bf04bf0e,0xbe79be95beacbec4,0xbd49bdc9be16be48,0xbf7dbf7fbf80bf80,0xbf71bf75bf78bf7b,0xbf5cbf62bf67bf6d,0xbf3ebf46bf4ebf55,
0x3f4e3f463f3e3f35,0x3f673f623f5c3f55,0x3f783f753f713f6d,0x3f803f7f3f7d3f7b,0x3e163dc93d498000,0x3eac3e953e793e48,0x3f043ef13edb3ec4,0x3f2c3f223f183f0e,
0x3f6a3f713f773f7b,0x3f423f4e3f583f62,0x3f7c3f783f733f6d,0x3f7e3f803f803f7f,0x3f393f2c3f1d3f0e,0x3f653f5c3f513f46,0x3e603e163d970000,0x3efc3edb3eb83e95,
0xbecfbeacbe89be48,0xbf27bf18bf09bef1,0x3e2f3e793ea13ec4,0xbdfbbd493cc93dc9,0x3f313f3e3f4a3f55,0x3ee63f043f133f22,0x3f7a3f7d3f7f3f80,0x3f5f3f673f6f3f75,
0x3f753f7b3f7f3f80,0x3f463f553f623f6d,0x3ef13f0e3f223f35,0x3dc93e483e953ec4,0xbe95be48bdc90000,0xbf22bf0ebef1bec4,0xbf62bf55bf46bf35,0xbf7fbf7bbf75bf6d,
0xbe95be48bdc98000,0xbf22bf0ebef1bec4,0xbf62bf55bf46bf35,0xbf7fbf7bbf75bf6d,0xbf75bf7bbf7fbf80,0xbf46bf55bf62bf6d,0xbef1bf0ebf22bf35,0xbdc9be48be95bec4,
0xbf7abf71bf65bf55,0xbf77bf7dbf80bf7f,0xbeb8be79bdfb0000,0xbf42bf2cbf13bef1,0x3e2f3d49bd97be48,0x3f1d3f043ecf3e95,0xbf39bf4ebf5fbf6d,0xbea1bedbbf09bf22,
0xbe60beacbee6bf0e,0x3e893e163cc9bdc9,0xbf6fbf78bf7ebf80,0xbf27bf3ebf51bf62,0x3f7c3f803f7f3f7b,0x3f4a3f5c3f6a3f75,0x3f313f183efc3ec4,0x3f733f673f583f46,
0x3f713f623f4e3f35,0x3f783f7f3f803f7b,0x3f2c3f463f5c3f6d,0x3e163e953edb3f0e,0xbf67bf75bf7dbf80,0xbf04bf22bf3ebf55,0x3d49bdc9be79bec4,0x3f183ef13eac3e48,
0x3eac3ef13f183f35,0xbe79bdc93d493e48,0xbf3ebf22bf04bec4,0xbf7dbf75bf67bf55,0x3edb3e953e168000,0x3f5c3f463f2c3f0e,0x3f803f7f3f783f6d,0x3f4e3f623f713f7b,
0xbf7fbf78bf6abf55,0xbf51bf67bf77bf7f,0xbdfb3d493e603ec4,0xbf39bf18bee6be95,0x3f733f7d3f803f7b,0x3f093f2c3f4a3f62,0x3efc3eac3e2f0000,0x3f6f3f5c3f423f22,
0xbd97be79becfbf0e,0x3f133edb3e893dc9,0xbf7ebf80bf7abf6d,0xbf31bf4ebf65bf75,0xbea1be163cc93e48,0xbf58bf3ebf1dbef1,0x3f5f3f713f7c3f80,0x3eb83f043f273f46,
0x3f553f6d3f7b3f80,0x3e483ec43f0e3f35,0xbf0ebec4be480000,0xbf7bbf6dbf55bf35,0xbf55bf6dbf7bbf80,0xbe48bec4bf0ebf35,0x3f0e3ec43e480000,0x3f7b3f6d3f553f35,
0xbf0ebec4be488000,0xbf7bbf6dbf55bf35,0xbf55bf6dbf7bbf80,0xbe48bec4bf0ebf35,0x3f0e3ec43e488000,0x3f7b3f6d3f553f35,0x3f553f6d3f7b3f80,0x3e483ec43f0e3f35,
0xbf27bf4ebf6abf7b,0x3e2fbd49be89bef1,0xbf1dbedbbe600000,0xbf80bf78bf65bf46,0x3ea13f043f313f55,0xbf09beacbdfb3dc9,0x3f5f3f3e3f133ec4,0x3f6f3f7d3f7f3f75,
0x3f423f183ecf3e48,0x3f7c3f803f773f62,0xbf4abf67bf7abf80,0xbcc9be79bee6bf22,0xbf73bf5cbf39bf0e,0xbf58bf71bf7ebf7f,0x3efc3f2c3f513f6d,0xbeb8be163d973e95,
0x3d493e953f043f35,0xbf4ebf22bedbbe48,0xbf71bf7fbf7dbf6d,0xbe79bef1bf2cbf55,0xbf3ebf62bf78bf80,0x3e16bdc9beacbf0e,0x3f673f463f183ec4,0x3f5c3f753f803f7b,
0xbf80bf75bf5cbf35,0xbf18bf46bf67bf7b,0x3eac3dc9be16bec4,0x3f783f623f3e3f0e,0x3f2c3ef13e798000,0x3f7d3f7f3f713f55,0x3edb3f223f4e3f6d,0xbf04be95bd493e48,
0x3f583f2c3ee63e48,0x3f5f3f783f803f75,0xbf6abf7dbf7ebf6d,0xbd97beacbf13bf46,0x3e2f3edb3f273f55,0xbf4abf18beb8bdc9,0x3f393f043e890000,0x3f733f803f7a3f62,
0x3f093f3e3f653f7b,0xbefcbe793cc93e95,0x3ecf3e16bdfbbec4,0x3f7f3f713f513f22,0xbf7cbf67bf42bf0e,0xbf1dbf4ebf6fbf7f,0x3f313f5c3f773f80,0xbea1bd493e603ef1,
0x3f223f553f753f80,0xbef1be483dc93ec4,0xbf7fbf7bbf62bf35,0xbe95bf0ebf46bf6d,0x3f463f0e3e950000,0x3f623f7b3f7f3f6d,0xbdc93e483ef13f35,0xbf75bf55bf22bec4,
0xbf46bf0ebe958000,0xbf62bf7bbf7fbf6d,0x3dc9be48bef1bf35,0x3f753f553f223ec4,0x3f223f553f753f80,0xbef1be483dc93ec4,0xbf7fbf7bbf62bf35,0xbe95bf0ebf46bf6d,
0x3eb83d49be89bf0e,0x3f7f3f783f583f22,0xbf51bf18bea10000,0xbf4abf71bf80bf75,0xbf39bf67bf7ebf7b,0x3ee63e16be2fbef1,0x3e603f043f423f6d,0xbf5fbf2cbecfbdc9,
0x3f6f3f803f773f55,0xbd973e793f093f46,0xbf13bf4ebf73bf80,0x3f1d3eac3cc9be95,0x3f313edb3dfbbe48,0x3f653f7d3f7c3f62,0xbf7abf5cbf27bec4,0xbefcbf3ebf6abf7f,
0xbf78bf7fbf67bf35,0x3d49be95bf18bf55,0x3f7d3f623f2c3ec4,0x3eac3f223f5c3f7b,0xbf04bf46bf71bf80,0x3f3e3ef13e16be48,0x3f4e3f753f803f6d,0xbedbbdc93e793f0e,
0x3e79bdc9bedbbf35,0x3f803f753f4e3f0e,0x3e163ef13f3e3f6d,0xbf71bf46bf04be48,0x3f5c3f223eac8000,0x3f2c3f623f7d3f7b,0xbf18be953d493ec4,0xbf67bf7fbf78bf55,
0xbefcbe163e603f0e,0xbf6abf80bf73bf46,0x3f273eacbcc9bec4,0x3f513f783f7e3f62,0xbf4abf04be2f3e48,0xbf31bf67bf7fbf75,0x3f653f2c3eb80000,0x3f093f4e3f773f7f,
0xbf5fbf7dbf7abf55,0x3ecf3d49bea1bf22,0x3f423f713f803f6d,0xbf13be793dfb3ef1,0xbf1dbf5cbf7cbf7b,0x3f393edb3d97be95,0x3ee63f3e3f6f3f80,0xbf58bf18be893dc9,
0x3ec43f353f6d3f80,0xbf6dbf35bec40000,0xbec4bf35bf6dbf80,0x3f6d3f353ec40000,0x3ec43f353f6d3f80,0xbf6dbf35bec40000,0xbec4bf35bf6dbf80,0x3f6d3f353ec40000,
0xbf6dbf35bec48000,0xbec4bf35bf6dbf80,0x3f6d3f353ec48000,0x3ec43f353f6d3f80,0xbf6dbf35bec48000,0xbec4bf35bf6dbf80,0x3f6d3f353ec48000,0x3ec43f353f6d3f80,
0x3f7e3f5c3f133e48,0x3cc93edb3f423f75,0xbf73bf3ebecf0000,0xbe60bf18bf5fbf7f,0x3f773f7d3f583f0e,0xbeb83d493ee63f46,0xbf7fbf71bf39bec4,0x3e2fbe79bf1dbf62,
0x3dfb3f043f513f7b,0xbf80bf67bf27be95,0xbea1bf2cbf6abf80,0x3f7a3f4e3efc3dc9,0xbe893e163f093f55,0xbf6fbf80bf65bf22,0x3d97beacbf31bf6d,0x3f7c3f783f4a3ef1,
0x3f043dc9beacbf35,0x3f3e3f753f7d3f55,0xbf4ebef1bd493ec4,0xbedbbf46bf78bf7b,0xbe79bf22bf67bf80,0x3f803f623f183e48,0xbe163e953f2c3f6d,0xbf71bf7fbf5cbf0e,
0x3f5c3f7f3f713f35,0xbf2cbe953e163f0e,0xbf18bf62bf80bf6d,0x3f673f223e79be48,0x3f783f463edb8000,0x3d493ef13f4e3f7b,0xbf7dbf75bf3ebec4,0x3eacbdc9bf04bf55,
0x3cc9bedbbf4abf7b,0x3f733f7d3f513ef1,0x3f093f5c3f7f3f6d,0xbf77bf3ebeb83dc9,0xbf6abf80bf5fbf0e,0x3f273e79be60bf22,0x3f7c3f4e3ee60000,0xbdfb3eac3f393f75,
0x3f803f673f1d3e48,0xbea13e163f133f62,0xbf58bf04bd973ec4,0xbe89bf2cbf6fbf7f,0x3ecfbd49befcbf55,0x3f423f783f7a3f46,0x3e2f3f183f653f80,0xbf7ebf71bf31be95,
0x3dc93f0e3f623f80,0xbf75bf7bbf46bec4,0x3f223e48be95bf35,0x3ef13f553f7f3f6d,0xbf7fbf55bef10000,0x3e95be48bf22bf6d,0x3f463f7b3f753f35,0xbf62bf0ebdc93ec4,
0xbf7fbf55bef18000,0x3e95be48bf22bf6d,0x3f463f7b3f753f35,0xbf62bf0ebdc93ec4,0xbdc9bf0ebf62bf80,0x3f753f7b3f463ec4,0xbf22be483e953f35,0xbef1bf55bf7fbf6d,
0x3f133f673f7f3f55,0xbf7ebf4ebecf3dc9,0xbf80bf5cbefc0000,0x3ee6bd49bf09bf62,0xbf7abf3ebea13e48,0x3e89be79bf31bf75,0x3eb8be16bf1dbf6d,0x3f273f713f7c3f46,
0xbf51bedb3d973f0e,0xbdfbbf18bf6abf7f,0xbcc9bf04bf5fbf80,0x3f653f803f583ef1,0xbe60bf2cbf73bf7b,0x3f773f783f393e95,0x3f6f3f7d3f4a3ec4,0xbf42beac3e2f3f22,
0x3f2c3f753f783f35,0xbf7dbf46beac3e48,0x3edbbdc9bf18bf6d,0x3f043f623f803f55,0x3d49bef1bf5cbf80,0x3f4e3f7f3f673f0e,0xbf71bf22be163ec4,0x3e79be95bf3ebf7b,
0xbf3ebe953e793f35,0xbe16bf22bf71bf7b,0x3f673f7f3f4e3ec4,0xbf5cbef13d493f0e,0x3f803f623f048000,0xbf18bdc93edb3f55,0xbeacbf46bf7dbf6d,0x3f783f753f2c3e48,
0x3ee63f5c3f803f55,0xbf7abf71bf1dbdc9,0xbf77bf2cbe2f3ec4,0x3ecfbe16bf27bf75,0xbd97bf18bf6fbf7b,0x3f513f803f5f3ef1,0x3f7e3f673f090000,0xbf39be793ea13f46,
0xbf65bf043cc93f0e,0x3e60beacbf4abf7f,0xbe89bf3ebf7cbf6d,0x3f6a3f7d3f423e95,0x3f7f3f4e3eb8be48,0xbf13bd493efc3f62,0xbdfb3edb3f583f80,0xbf31bf78bf73bf22,
0xbe483ec43f553f80,0xbf0ebf6dbf7bbf35,0x3f7b3f6d3f0e0000,0xbf55bec43e483f35,0x3e48bec4bf55bf80,0x3f0e3f6d3f7b3f35,0xbf7bbf6dbf0e0000,0x3f553ec4be48bf35,
0xbf7bbf6dbf0e8000,0x3f553ec4be48bf35,0xbe483ec43f553f80,0xbf0ebf6dbf7bbf35,0x3f7b3f6d3f0e8000,0xbf55bec43e483f35,0x3e48bec4bf55bf80,0x3f0e3f6d3f7b3f35,
0xbee63e163f313f7b,0xbe60bf3ebf7ebf62,0xbf77bf71bf130000,0x3f6a3f04bd97bf22,0x3f423e79beb8bf55,0xbe2f3edb3f5f3f7f,0x3f4a3f803f583ec4,0xbf80bf4ebea13e95,
0xbf65bf7dbf39be48,0x3f7a3f2c3dfbbef1,0x3e89beacbf51bf80,0x3ecf3f5c3f7f3f46,0x3f273f783f6f3f0e,0xbf7cbf67befc3dc9,0xbf1dbd493f093f6d,0xbcc9bf18bf73bf75,
0xbf67bef13e163f35,0x3f04bdc9bf2cbf7b,0x3d493f223f783f6d,0xbf18bf75bf71bf0e,0x3eacbe95bf4ebf80,0x3e793f463f803f55,0xbf3ebf7fbf5cbec4,0x3f7d3f623edbbe48,
0xbedbbf62bf7dbf35,0x3f5c3f7f3f3e3e48,0xbf80bf46be793ec4,0x3f4e3e95beacbf55,0x3f713f753f188000,0xbf78bf22bd493f0e,0x3f2c3dc9bf04bf6d,0xbe163ef13f673f7b,
0xbf51bf80bf42be48,0x3f7e3f5c3eb8be95,0x3cc9bf18bf77bf6d,0x3ee63f673f7a3f22,0x3f583eacbea1bf55,0xbefc3e163f393f7f,0x3f6a3f783f1d0000,0xbf7fbf3ebe2f3ef1,
0x3f13bd49bf27bf7b,0xbdfb3f043f6f3f75,0x3f803f4e3e89bec4,0xbf65bedb3e603f46,0x3f093f713f733f0e,0xbf5fbf7dbf31bdc9,0xbecf3e793f4a3f80,0xbd97bf2cbf7cbf62,
0xbef13e483f463f80,0x3dc9bf0ebf75bf6d,0x3e953f553f7f3f35,0xbf22bf7bbf62bec4,0x3f623f7b3f220000,0xbf7fbf55be953ec4,0x3f753f0ebdc9bf35,0xbf46be483ef13f6d,
0xbf62bf7bbf228000,0x3f7f3f553e95bec4,0xbf75bf0e3dc93f35,0x3f463e48bef1bf6d,0xbef13e483f463f80,0x3dc9bf0ebf75bf6d,0x3e953f553f7f3f35,0xbf22bf7bbf62bec4,
0xbf80bf3ebdfb3f0e,0x3f733f04be2fbf46,0xbf58bf7dbf270000,0x3f773f673ecfbe95,0xbeb83eac3f5f3f7b,0x3d97bf18bf7abf62,0xbf51be793ee63f6d,0x3f1dbd49bf31bf7f,
0xbcc9bf2cbf7ebf55,0x3ea13f5c3f7c3f22,0x3f09be16bf42bf80,0xbe893edb3f6a3f75,0xbf6fbf71befc3e48,0x3f7f3f4e3e60bef1,0xbf13bf78bf65bec4,0x3f4a3f803f393dc9,
0xbe16bf46bf80bf35,0x3eac3f623f783f0e,0xbf04bf75bf67bec4,0x3f2c3f7f3f4e3e48,0x3f18bdc9bf3ebf80,0xbedb3e953f5c3f7b,0x3e79bef1bf71bf6d,0xbd493f223f7d3f55,
0x3f7d3f22bd49bf35,0xbf71bef13e793f55,0x3f5c3e95bedbbf6d,0xbf3ebdc93f183f7b,0x3f4e3f7f3f2c8000,0xbf67bf75bf043e48,0x3f783f623eacbec4,0xbf80bf46be163f0e,
0x3f7e3f4e3e2fbf0e,0xbf80bf3ebd973f22,0x3f733f673eb8bec4,0xbf7abf5cbe893ef1,0x3f5f3f783f09be48,0xbf6abf71bee63e95,0x3f423f803f310000,0xbf51bf7dbf1d3dc9,
0xbdfb3f183f7c3f55,0x3cc9bf2cbf7fbf46,0xbea13edb3f6f3f6d,0x3e60bf04bf77bf62,0xbefc3e793f583f7b,0x3ecfbeacbf65bf75,0xbf273d493f393f80,0x3f13be16bf4abf7f,
0x3f003f003f003f00,0x3f003f003f003f00,0x3f003f003f003f00,0x3f003f003f003f00,0x3f003f003f003f00,0x3f003f003f003f00,0x3f003f003f003f00,0x3f003f003f003f00,
0xbf003f00bf003f00,0xbf003f00bf003f00,0xbf003f00bf003f00,0xbf003f00bf003f00,0xbf003f00bf003f00,0xbf003f00bf003f00,0xbf003f00bf003f00,0xbf003f00bf003f00,
0xbf5fbf5cbf58bf55,0xbf6abf67bf65bf62,0xbf42bf3ebf39bf35,0xbf51bf4ebf4abf46,0xbf7ebf7dbf7cbf7b,0xbf80bf80bf7fbf7f,0xbf73bf71bf6fbf6d,0xbf7abf78bf77bf75,
0xbefcbf04bf09bf0e,0xbecfbedbbee6bef1,0xbf27bf2cbf31bf35,0xbf13bf18bf1dbf22,0xbdfbbe16be2fbe48,0xbcc9bd49bd97bdc9,0xbea1beacbeb8bec4,0xbe60be79be89be95,
0x3f4e3f463f3e3f35,0x3f673f623f5c3f55,0x3f783f753f713f6d,0x3f803f7f3f7d3f7b,0x3e163dc93d490000,0x3eac3e953e793e48,0x3f043ef13edb3ec4,0x3f2c3f223f183f0e,
0x3f183f223f2c3f35,0x3edb3ef13f043f0e,0x3e793e953eac3ec4,0x3d493dc93e163e48,0x3f7d3f7f3f803f80,0x3f713f753f783f7b,0x3f5c3f623f673f6d,0x3f3e3f463f4e3f55,
0xbf6fbf67bf5fbf55,0xbf7fbf7dbf7abf75,0xbf13bf04bee6bec4,0xbf4abf3ebf31bf22,0xbcc93d493dfb3e48,0xbea1be79be2fbdc9,0x3f093f183f273f35,0x3e893eac3ecf3ef1,
0xbeb8bedbbefcbf0e,0xbd97be16be60be95,0xbf51bf5cbf65bf6d,0xbf1dbf2cbf39bf46,0xbf80bf80bf7ebf7b,0xbf73bf78bf7cbf7f,0xbf58bf4ebf42bf35,0xbf77bf71bf6abf62,
0xbf75bf7bbf7fbf80,0xbf46bf55bf62bf6d,0xbef1bf0ebf22bf35,0xbdc9be48be95bec4,0x3e953e483dc90000,0x3f223f0e3ef13ec4,0x3f623f553f463f35,0x3f7f3f7b3f753f6d,
0x3e953e483dc98000,0x3f223f0e3ef13ec4,0x3f623f553f463f35,0x3f7f3f7b3f753f6d,0x3f753f7b3f7f3f80,0x3f463f553f623f6d,0x3ef13f0e3f223f35,0x3dc93e483e953ec4,
0x3f583f673f733f7b,0x3efc3f183f313f46,0x3f6a3f5c3f4a3f35,0x3f7f3f803f7c3f75,0xbf51bf3ebf27bf0e,0xbf7ebf78bf6fbf62,0x3cc93e163e893ec4,0xbee6beacbe60bdc9,
0xbf09bedbbea1be48,0xbf5fbf4ebf39bf22,0x3ecf3f043f1d3f35,0xbd973d493e2f3e95,0xbf13bf2cbf42bf55,0xbdfbbe79beb8bef1,0xbf80bf7dbf77bf6d,0xbf65bf71bf7abf7f,
0xbeacbef1bf18bf35,0x3e793dc9bd49be48,0x3f3e3f223f043ec4,0x3f7d3f753f673f55,0xbedbbe95be160000,0xbf5cbf46bf2cbf0e,0xbf80bf7fbf78bf6d,0xbf4ebf62bf71bf7b,
0x3f713f623f4e3f35,0x3f783f7f3f803f7b,0x3f2c3f463f5c3f6d,0x3e163e953edb3f0e,0xbf67bf75bf7dbf80,0xbf04bf22bf3ebf55,0x3d49bdc9be79bec4,0x3f183ef13eac3e48,
0xbf27bf04beb8be48,0xbf7cbf71bf5fbf46,0x3f1d3f3e3f583f6d,0xbcc93e163ea13ef1,0x3f653f4e3f313f0e,0x3f7a3f803f7e3f75,0xbe89bedbbf13bf35,0x3ecf3e793d97bdc9,
0xbf42bf5cbf6fbf7b,0xbe2fbeacbefcbf22,0xbf4abf2cbf09bec4,0xbf80bf7dbf73bf62,0x3ee63f183f393f55,0xbe60bd493dfb3e95,0x3f773f673f513f35,0x3f6a3f783f7f3f7f,
0x3f553f6d3f7b3f80,0x3e483ec43f0e3f35,0xbf0ebec4be480000,0xbf7bbf6dbf55bf35,0xbf55bf6dbf7bbf80,0xbe48bec4bf0ebf35,0x3f0e3ec43e480000,0x3f7b3f6d3f553f35,
0xbf0ebec4be488000,0xbf7bbf6dbf55bf35,0xbf55bf6dbf7bbf80,0xbe48bec4bf0ebf35,0x3f0e3ec43e488000,0x3f7b3f6d3f553f35,0x3f553f6d3f7b3f80,0x3e483ec43f0e3f35,
0x3d97be16beb8bf0e,0x3f513f2c3efc3e95,0xbf7ebf71bf58bf35,0xbf39bf5cbf73bf7f,0xbee6be79bcc93e48,0xbf7abf67bf4abf22,0x3f773f803f7c3f6d,0x3ecf3f183f423f62,
0x3f7f3f7d3f6f3f55,0x3f133f3e3f5f3f75,0xbdfbbeacbf09bf35,0x3f313f043ea13dc9,0xbf65bf78bf80bf7b,0xbe60bedbbf1dbf46,0xbe89bd493e2f3ec4,0xbf6abf4ebf27bef1,
0xbf80bf75bf5cbf35,0xbf18bf46bf67bf7b,0x3eac3dc9be16bec4,0x3f783f623f3e3f0e,0x3f2c3ef13e790000,0x3f7d3f7f3f713f55,0x3edb3f223f4e3f6d,0xbf04be95bd493e48,
0xbd49be95bf04bf35,0x3f4e3f223edb3e48,0x3f713f7f3f7d3f6d,0x3e793ef13f2c3f55,0x3f3e3f623f783f80,0xbe163dc93eac3f0e,0xbf67bf46bf18bec4,0xbf5cbf75bf80bf7b,
0xbe603d493ea13f0e,0xbf77bf5cbf31bef1,0x3f6f3f4e3f1d3ec4,0x3f423f673f7c3f7f,0xbf51bf71bf7fbf7b,0x3dfbbe16becfbf22,0xbcc93e793efc3f35,0xbf65bf3ebf09be95,
0xbf7abf80bf73bf55,0xbe89bf04bf39bf62,0x3eb83f183f4a3f6d,0xbf27bedbbe2f3dc9,0x3f133eac3d97be48,0x3f7e3f7d3f6a3f46,0xbf80bf78bf5fbf35,0xbee6bf2cbf58bf75,
0xbf22bf55bf75bf80,0x3ef13e48bdc9bec4,0x3f7f3f7b3f623f35,0x3e953f0e3f463f6d,0xbf46bf0ebe950000,0xbf62bf7bbf7fbf6d,0x3dc9be48bef1bf35,0x3f753f553f223ec4,
0x3f463f0e3e958000,0x3f623f7b3f7f3f6d,0xbdc93e483ef13f35,0xbf75bf55bf22bec4,0xbf22bf55bf75bf80,0x3ef13e48bdc9bec4,0x3f7f3f7b3f623f35,0x3e953f0e3f463f6d,
0xbf6abf3ebefcbe48,0xbf27bf5cbf7abf7f,0x3f7c3f7d3f653f35,0x3dfb3edb3f313f62,0x3cc93eac3f1d3f55,0xbf73bf4ebf13be95,0x3f093e79bd97bec4,0x3f773f803f6f3f46,
0xbecfbf2cbf5fbf7b,0x3f423f043e60bdc9,0xbe2f3e163ee63f35,0xbf7ebf67bf39bef1,0xbf80bf71bf4abf0e,0xbea1bf18bf51bf75,0x3f583f783f7f3f6d,0xbe893d493eb83f22,
0xbe793dc93edb3f35,0xbf80bf75bf4ebf0e,0xbe16bef1bf3ebf6d,0x3f713f463f043e48,0xbf5cbf22beac0000,0xbf2cbf62bf7dbf7b,0x3f183e95bd49bec4,0x3f673f7f3f783f55,
0xbf78bf7fbf67bf35,0x3d49be95bf18bf55,0x3f7d3f623f2c3ec4,0x3eac3f223f5c3f7b,0xbf04bf46bf71bf80,0x3f3e3ef13e16be48,0x3f4e3f753f803f6d,0xbedbbdc93e793f0e,
0x3e893f183f583f7b,0xbf6fbf3ebee6bdc9,0xbd97bedbbf39bf6d,0x3f7c3f5c3f1d3e95,0xbdfb3e793f133f55,0xbf80bf71bf42bef1,0x3ea1bd49becfbf35,0x3f7a3f7d3f5f3f22,
0xbf77bf4ebf09be48,0xbeb8bf2cbf65bf7f,0x3f7f3f673f313ec4,0x3e2f3f043f4a3f75,0xbf7ebf78bf51bf0e,0x3cc9beacbf27bf62,0x3f733f803f6a3f35,0xbe603e163efc3f46,
0x3ec43f353f6d3f80,0xbf6dbf35bec40000,0xbec4bf35bf6dbf80,0x3f6d3f353ec40000,0x3ec43f353f6d3f80,0xbf6dbf35bec40000,0xbec4bf35bf6dbf80,0x3f6d3f353ec40000,
0xbf6dbf35bec48000,0xbec4bf35bf6dbf80,0x3f6d3f353ec48000,0x3ec43f353f6d3f80,0xbf6dbf35bec48000,0xbec4bf35bf6dbf80,0x3f6d3f353ec48000,0x3ec43f353f6d3f80,
0x3f4a3f783f7c3f55,0xbf31beac3d973ef1,0xbf65bf80bf6fbf35,0x3f093e16be89bf22,0x3efc3f4e3f7a3f7b,0xbf6abf2cbea13dc9,0xbf27bf67bf80bf6d,0x3f513f043dfbbe95,
0xbf1dbe793e2f3f0e,0xbf39bf71bf7fbf62,0x3ee63d49beb8bf35,0x3f583f7d3f773f46,0xbf5fbf18be603e48,0xbecfbf3ebf73bf7f,0x3f423edb3cc9bec4,0x3f133f5c3f7e3f75,
0x3f5c3f7f3f713f35,0xbf2cbe953e163f0e,0xbf18bf62bf80bf6d,0x3f673f223e79be48,0x3f783f463edb0000,0x3d493ef13f4e3f7b,0xbf7dbf75bf3ebec4,0x3eacbdc9bf04bf55,
0xbf04bdc93eac3f35,0xbf3ebf75bf7dbf55,0x3f4e3ef13d49bec4,0x3edb3f463f783f7b,0x3e793f223f673f80,0xbf80bf62bf18be48,0x3e16be95bf2cbf6d,0x3f713f7f3f5c3f0e,
0x3f313f713f7e3f55,0xbf65bf18be2f3e95,0xbf7abf78bf42bec4,0x3efc3d49becfbf46,0x3f6f3f2c3e89be48,0x3d973f043f583f7f,0xbf13be163ea13f35,0xbf1dbf67bf80bf62,
0xbf39beac3dfb3f0e,0xbee6bf4ebf7cbf75,0x3e60be79bf27bf6d,0x3f5f3f803f6a3f22,0x3eb83f3e3f773f7b,0xbf7fbf5cbf09bdc9,0xbf51bf7dbf73bf35,0x3f4a3edbbcc9bef1,
0xbdc9bf0ebf62bf80,0x3f753f7b3f463ec4,0xbf22be483e953f35,0xbef1bf55bf7fbf6d,0x3f7f3f553ef10000,0xbe953e483f223f6d,0xbf46bf7bbf75bf35,0x3f623f0e3dc9bec4,
0x3f7f3f553ef18000,0xbe953e483f223f6d,0xbf46bf7bbf75bf35,0x3f623f0e3dc9bec4,0x3dc93f0e3f623f80,0xbf75bf7bbf46bec4,0x3f223e48be95bf35,0x3ef13f553f7f3f6d,
0x3e2fbeacbf42bf7b,0x3f4a3f7d3f6f3f22,0x3f393f783f773f35,0xbf73bf2cbe603e95,0x3f583f803f653f0e,0xbf5fbf04bcc93ef1,0xbf6abf18bdfb3ec4,0x3d97bedbbf51bf7f,
0x3f7c3f713f273e48,0xbf1dbe163eb83f46,0xbf31be793e893f35,0xbea1bf3ebf7abf75,0xbf09bd493ee63f55,0xbefcbf5cbf80bf62,0xbecfbf4ebf7ebf6d,0x3f7f3f673f133dc9,
0x3f3e3e95be79bf35,0x3e163f223f713f7b,0xbf67bf7fbf4ebec4,0x3f5c3ef1bd49bf0e,0xbf80bf62bf040000,0x3f183dc9bedbbf55,0x3eac3f463f7d3f6d,0xbf78bf75bf2cbe48,
0x3f2c3f753f783f35,0xbf7dbf46beac3e48,0x3edbbdc9bf18bf6d,0x3f043f623f803f55,0x3d49bef1bf5cbf80,0x3f4e3f7f3f673f0e,0xbf71bf22be163ec4,0x3e79be95bf3ebf7b,
0x3f733f783f313e48,0xbf58bedb3dfb3f22,0xbefc3d493f133f6d,0xbeb8bf4ebf7fbf62,0xbf42bf7dbf6abf0e,0x3f7c3f3e3e89be95,0x3f4a3eacbe60bf35,0xbcc93f043f653f7f,
0xbea13e793f393f7b,0xbf09bf67bf7ebf46,0xbf5fbf80bf51bec4,0x3f6f3f183d97bef1,0x3f273e16becfbf55,0x3e2f3f2c3f773f75,0x3f1d3f713f7a3f35,0xbf80bf5cbee63dc9,
0xbe483ec43f553f80,0xbf0ebf6dbf7bbf35,0x3f7b3f6d3f0e0000,0xbf55bec43e483f35,0x3e48bec4bf55bf80,0x3f0e3f6d3f7b3f35,0xbf7bbf6dbf0e0000,0x3f553ec4be48bf35,
0xbf7bbf6dbf0e8000,0x3f553ec4be48bf35,0xbe483ec43f553f80,0xbf0ebf6dbf7bbf35,0x3f7b3f6d3f0e8000,0xbf55bec43e483f35,0x3e48bec4bf55bf80,0x3f0e3f6d3f7b3f35,
0xbf73bf18bcc93f0e,0x3f09bd49bf1dbf75,0xbefcbf67bf7cbf35,0x3f6f3f783f273dc9,0x3f7f3f5c3ecfbe48,0xbf51beac3e893f46,0x3dfb3f2c3f7a3f6d,0xbf39bf7dbf65bef1,
0xbea1bf4ebf80bf55,0x3f583f803f4a3e95,0x3f5f3edbbe2fbf35,0xbeb83e793f423f7f,0xbd973f043f6a3f7b,0xbf13bf71bf77bf22,0xbf7ebf3ebe603ec4,0x3f313e16bee6bf62,
0xbedbbf62bf7dbf35,0x3f5c3f7f3f3e3e48,0xbf80bf46be793ec4,0x3f4e3e95beacbf55,0x3f713f753f180000,0xbf78bf22bd493f0e,0x3f2c3dc9bf04bf6d,0xbe163ef13f673f7b,
0x3f673ef1be16bf35,0xbf043dc93f2c3f7b,0xbd49bf22bf78bf6d,0x3f183f753f713f0e,0xbeac3e953f4e3f80,0xbe79bf46bf80bf55,0x3f3e3f7f3f5c3ec4,0xbf7dbf62bedb3e48,
0x3f7c3f2c3d97bf0e,0xbf4abe793ecf3f62,0x3f313f7d3f5f3ec4,0xbf73bf71bf093dc9,0xbe603edb3f653f7b,0xbe89bf4ebf80bf46,0xbf6fbf043dfb3f35,0x3f273d49bf13bf75,
0x3e2f3f3e3f7f3f55,0xbf1dbf78bf6abef1,0xbf39be163efc3f6d,0x3ea1beacbf58bf7f,0xbf7abf67bee63e48,0x3f773f18bcc9bf22,0xbeb8bf5cbf7ebf35,0x3f423f803f513e95,
0x3ef1be48bf46bf80,0xbdc93f0e3f753f6d,0xbe95bf55bf7fbf35,0x3f223f7b3f623ec4,0xbf62bf7bbf220000,0x3f7f3f553e95bec4,0xbf75bf0e3dc93f35,0x3f463e48bef1bf6d,
0x3f623f7b3f228000,0xbf7fbf55be953ec4,0x3f753f0ebdc9bf35,0xbf46be483ef13f6d,0x3ef1be48bf46bf80,0xbdc93f0e3f753f6d,0xbe95bf55bf7fbf35,0x3f223f7b3f623ec4,
0x3f393f803f4a3e48,0xbf65bf78bf133dc9,0x3e603f4e3f7f3f35,0xbefcbf71bf6fbef1,0x3f6a3edbbe89bf55,0xbf42be163f093f75,0x3f7c3f5c3ea1bec4,0xbf7ebf2cbcc93f22,
0xbf31bd493f1d3f7b,0x3ee6be79bf51bf7f,0xbf7abf183d973f35,0x3f5f3eacbeb8bf62,0x3ecf3f673f773f0e,0xbf27bf7dbf58be95,0xbe2f3f043f733f6d,0xbdfbbf3ebf80bf46,
0xbf7dbf223d493f35,0x3f713ef1be79bf55,0xbf5cbe953edb3f6d,0x3f3e3dc9bf18bf7b,0xbf4ebf7fbf2c0000,0x3f673f753f04be48,0xbf78bf62beac3ec4,0x3f803f463e16bf0e,
0xbe16bf46bf80bf35,0x3eac3f623f783f0e,0xbf04bf75bf67bec4,0x3f2c3f7f3f4e3e48,0x3f18bdc9bf3ebf80,0xbedb3e953f5c3f7b,0x3e79bef1bf71bf6d,0xbd493f223f7d3f55,
0x3f4a3e16bf13bf7b,0xbf39bd493f273f7f,0x3f653eacbecfbf6d,0xbf58be793efc3f75,0x3f773f04be60bf55,0xbf6fbedb3ea13f62,0x3f7f3f2cbcc9bf35,0xbf7cbf183dfb3f46,
0x3f1d3f7d3f513e48,0xbf31bf80bf42bdc9,0x3ee63f713f6a3ec4,0xbf09bf78bf5fbe95,0x3e893f5c3f7a3f0e,0xbeb8bf67bf73bef1,0x3d973f3e3f803f35,0xbe2fbf4ebf7ebf22,
0xbf8000003f80,0xbf8000003f80,0xbf8000003f80,0xbf8000003f80,0xbf8000003f80,0xbf8000003f80,0xbf8000003f80,0xbf8000003f80,
0x3f808000bf808000,0x3f808000bf808000,0x3f808000bf808000,0x3f808000bf808000,0x3f808000bf808000,0x3f808000bf808000,0x3f808000bf808000,0x3f808000bf808000,
0x3f773e79bf7abe48,0x3f6f3eacbf73be95,0x3f7f3d49bf800000,0x3f7c3e16bf7ebdc9,0x3f4a3f18bf51bf0e,0x3f393f2cbf42bf22,0x3f653edbbf6abec4,0x3f583f04bf5fbef1,
0xbe893f783e60bf7b,0xbeb83f713ea1bf75,0xbd973f803cc9bf80,0xbe2f3f7d3dfbbf7f,0xbf1d3f4e3f13bf55,0xbf313f3e3f27bf46,0xbee63f673ecfbf6d,0xbf093f5c3efcbf62,
0xbf4e3f223f3ebf35,0xbf673ef13f5cbf0e,0xbf783e953f71bec4,0xbf803dc93f7dbe48,0xbe163f7f3d49bf80,0xbeac3f753e79bf7b,0xbf043f623edbbf6d,0xbf2c3f463f18bf55,
0xbf18bf463f2c3f35,0xbedbbf623f043f55,0xbe79bf753eac3f6d,0xbd49bf7f3e163f7b,0xbf7dbdc93f808000,0xbf71be953f783e48,0xbf5cbef13f673ec4,0xbf3ebf223f4e3f0e,
0x3ecfbf71be893f7b,0x3f27bf4ebf093f62,0xbe2fbf783ea13f6d,0x3dfbbf803cc93f7f,0xbf31bf2c3f4a3f0e,0xbee6bf5c3f133f46,0xbf7abe163f7f0000,0xbf5fbedb3f6f3e95,
0x3f6a3eacbf77be48,0x3f423f18bf58bef1,0x3f7cbe79bf733ec4,0x3f7e3d49bf803dc9,0x3f39bf3ebf1d3f55,0x3f65bf04bf513f22,0x3e60bf7dbd973f80,0x3efcbf67beb83f75,
0x3e95bf7bbdc93f80,0x3f22bf55bef13f6d,0x3f62bf0ebf463f35,0x3f7fbe48bf753ec4,0x3f753e48bf7f0000,0x3f463f0ebf62bec4,0x3ef13f55bf22bf35,0x3dc93f7bbe95bf6d,
0x3f753e48bf7f8000,0x3f463f0ebf62bec4,0x3ef13f55bf22bf35,0x3dc93f7bbe95bf6d,0xbe953f7b3dc9bf80,0xbf223f553ef1bf6d,0xbf623f0e3f46bf35,0xbf7f3e483f75bec4,
0x3e603f71bee6bf55,0xbe893f7d3cc9bf7f,0x3f6f3e79bf7e0000,0x3f273f2cbf51bef1,0xbf7cbd493f7fbe48,0xbf4abf043f6a3e95,0xbf313f4e3efcbf6d,0xbf733edb3f58bf22,
0xbf7a3eac3f65bf0e,0xbf77be163f80bdc9,0xbeb83f783dfbbf80,0xbf423f3e3f13bf62,0x3e2fbf803d973f7b,0x3f1dbf5cbecf3f75,0xbf39bf183f5f3ec4,0xbea1bf673f093f46,
0xbeacbf623f183f35,0x3e79bf7f3d493f7b,0x3f3ebf46bf043f6d,0x3f7dbe95bf673f0e,0xbedb3f753e16bf80,0xbf5c3f223f2cbf55,0xbf803dc93f78bec4,0xbf4ebef13f713e48,
0x3f71bef1bf4e3f35,0x3f783dc9bf803e48,0x3f2c3f22bf5cbec4,0x3e163f75bedbbf55,0xbf67be953f7d8000,0xbf04bf463f3e3f0e,0x3d49bf7f3e793f6d,0x3f18bf62beac3f7b,
0x3d973f78becfbf55,0xbf133f673e89bf7f,0x3f7ebd49bf7a3ec4,0x3f313f18bf65be95,0x3ea1bf7d3cc93f7b,0x3f58bf2cbf1d3f62,0xbf5fbeac3f7c0000,0xbeb8bf5c3f273f22,
0xbf7f3e793f6abf0e,0xbf51bedb3f773dc9,0xbdfb3f80be60bf6d,0xbf393f4e3ee6bf75,0x3f733e16bf803e48,0x3f093f3ebf4abef1,0x3efcbf71be2f3f80,0x3f6fbf04bf423f46,
0x3f0ebf6dbe483f80,0x3f7bbec4bf553f35,0x3f553ec4bf7b0000,0x3e483f6dbf0ebf35,0xbf0e3f6d3e48bf80,0xbf7b3ec43f55bf35,0xbf55bec43f7b0000,0xbe48bf6d3f0e3f35,
0x3f553ec4bf7b8000,0x3e483f6dbf0ebf35,0xbf0e3f6d3e48bf80,0xbf7b3ec43f55bf35,0xbf55bec43f7b8000,0xbe48bf6d3f0e3f35,0x3f0ebf6dbe483f80,0x3f7bbec4bf553f35,
0xbf423f4e3ecfbf7b,0xbf7c3d493f77bef1,0x3f4a3edbbf7a0000,0x3cc93f78bee6bf46,0x3f73bf04bf393f55,0x3f583eacbf7e3dc9,0xbefcbf3e3f513ec4,0x3eb8bf7d3d973f75,
0xbf27bf183f6a3e48,0x3e2fbf803e893f62,0xbf1d3f673e60bf80,0xbf803e793f65bf22,0x3ea13f5cbf31bf0e,0xbf093f713dfbbf7f,0x3f5fbf2cbf133f6d,0x3f6f3e16bf7f3e95,
0x3f80be95bf5c3f35,0x3f183f22bf67be48,0xbeac3f7fbe16bf6d,0xbf783ef13f3ebf55,0xbf2c3f623e79bf80,0xbf7d3dc93f71bf0e,0xbedbbf463f4e3ec4,0x3f04bf75bd493f7b,
0x3d493f75bf04bf35,0xbf4e3f463edbbf7b,0xbf71bdc93f7dbec4,0xbe79bf623f2c3f0e,0xbf3ebef13f788000,0x3e16bf7f3eac3f55,0x3f67bf22bf183f6d,0x3f5c3e95bf803e48,
0xbf09bf2c3f653e48,0x3efcbf783cc93f75,0xbecf3f7dbdfbbf6d,0xbf7f3eac3f51bf46,0x3f7cbedbbf423f55,0x3f1d3f18bf6fbdc9,0xbf31bf043f770000,0x3ea1bf803e603f62,
0x3f58bf3ebee63f7b,0x3f5f3e79bf803e95,0xbf6abe163f7ebec4,0xbd97bf713f133f22,0x3e2f3f67bf27bf0e,0xbf4a3f4e3eb8bf7f,0x3f39bf5cbe893f80,0x3f733d49bf7a3ef1,
0x3f46bf55be953f80,0x3f623e48bf7f3ec4,0xbdc93f7bbef1bf35,0xbf753f0e3f22bf6d,0xbf22bf0e3f750000,0x3ef1bf7b3dc93f6d,0x3f7fbe48bf623f35,0x3e953f55bf46bec4,
0x3f223f0ebf758000,0xbef13f7bbdc9bf6d,0xbf7f3e483f62bf35,0xbe95bf553f463ec4,0x3f46bf55be953f80,0x3f623e48bf7f3ec4,0xbdc93f7bbef1bf35,0xbf753f0e3f22bf6d,
0xbf6fbd493f77bf0e,0x3d97bf783f093f22,0x3f133f18bf730000,0xbf1d3f713cc9bf75,0xbf313f673dfbbf7b,0xbf65be163f7cbef1,0x3f7abf04bf273f6d,0x3efc3f2cbf6abdc9,
0x3eb8bf803e893f55,0x3f7fbe79bf583f46,0xbf513f4e3ea1bf80,0xbf4abeac3f80be95,0xbf39bedb3f7ebe48,0x3ee6bf7d3e2f3f62,0x3e603f5cbf42bec4,0xbf5f3f3e3ecfbf7f,
0xbe793f7fbedbbf35,0xbf803e953f4ebf55,0xbe16bf623f3e3ec4,0x3f71bf22bf043f7b,0xbf5c3f463eacbf80,0xbf2cbef13f7dbe48,0x3f18bf753d493f6d,0x3f673dc9bf783f0e,
0xbf783dc93f67bf35,0x3d49bf753f183f0e,0x3f7dbef1bf2c3f6d,0x3eac3f46bf5cbe48,0xbf04bf223f718000,0x3f3ebf62be163f7b,0x3f4e3e95bf803ec4,0xbedb3f7fbe79bf55,
0x3f5f3e16bf7a3f0e,0xbecf3f80bea1bf46,0xbf42beac3f80bec4,0x3f13bf783dfb3f62,0x3f1d3f04bf7c3e48,0xbf393f673d97bf75,0xbee6bf2c3f6f0000,0x3f58bf4ebe893f7f,
0xbefc3f7dbe60bf55,0xbf6abd493f73bf22,0x3f27bf713cc93f6d,0x3f513e79bf7e3ef1,0xbf4a3f5c3e2fbf7b,0xbf31bedb3f7fbe95,0x3f65bf3ebeb83f80,0x3f093f18bf773dc9,
0x3f6dbf35bec43f80,0x3ec43f35bf6d0000,0xbf6d3f353ec4bf80,0xbec4bf353f6d0000,0x3f6dbf35bec43f80,0x3ec43f35bf6d0000,0xbf6d3f353ec4bf80,0xbec4bf353f6d0000,
0x3ec43f35bf6d8000,0xbf6d3f353ec4bf80,0xbec4bf353f6d8000,0x3f6dbf35bec43f80,0x3ec43f35bf6d8000,0xbf6d3f353ec4bf80,0xbec4bf353f6d8000,0x3f6dbf35bec43f80,
0xbdfbbf5c3f513e48,0x3f80bedbbf273f75,0x3ea13f3ebf6a0000,0xbf7a3f183efcbf7f,0x3e89bf7d3f093f0e,0x3f6fbd49bf653f46,0xbd973f71bf31bec4,0xbf7c3e793f4abf62,
0x3f7ebf04bf133f7b,0x3cc93f67bf42be95,0xbf733f2c3ecfbf80,0xbe60bf4e3f5f3dc9,0x3f77be16bf583f55,0xbeb83f80bee6bf22,0xbf7f3eac3f39bf6d,0x3e2fbf783f1d3ef1,
0xbf5cbdc93f71bf35,0x3f2cbf753e163f55,0x3f183ef1bf803ec4,0xbf673f463e79bf7b,0xbf783f223edbbf80,0xbd49bf623f4e3e48,0x3f7dbe95bf3e3f6d,0xbeac3f7fbf04bf0e,
0x3f04bf7f3eac3f35,0x3f3e3e95bf7d3f0e,0xbf4e3f623d49bf6d,0xbedbbf223f78be48,0xbe79bf463f678000,0x3f80bef1bf183f7b,0xbe163f75bf2cbec4,0xbf713dc93f5cbf55,
0xbf803edb3f1dbf7b,0x3ea1bf7d3f133ef1,0x3f58bf5cbd973f6d,0x3e893f3ebf6f3dc9,0xbecf3f80befcbf0e,0xbf42be793f7abf22,0xbe2fbf4e3f650000,0x3f7ebeacbf313f75,
0x3cc9bf673f4a3e48,0x3f73be16bf513f62,0x3f093f04bf7f3ec4,0xbf773f2c3eb8bf7f,0xbf6a3d493f5fbf55,0x3f27bf783e603f46,0x3f7cbf18bee63f80,0xbdfb3f71bf39be95,
0x3f7fbf0ebef13f80,0xbe953f7bbf22bec4,0xbf46be483f75bf35,0x3f62bf55bdc93f6d,0x3dc93f55bf620000,0xbf753e483f46bf6d,0x3f22bf7b3e953f35,0x3ef13f0ebf7f3ec4,
0x3dc93f55bf628000,0xbf753e483f46bf6d,0x3f22bf7b3e953f35,0x3ef13f0ebf7f3ec4,0xbf7f3f0e3ef1bf80,0x3e95bf7b3f223ec4,0x3f463e48bf753f35,0xbf623f553dc9bf6d,
0x3f51bf673d973f55,0x3dfb3f4ebf6a3dc9,0x3cc93f5cbf5f0000,0xbf653d493f58bf62,0x3e603f3ebf733e48,0xbf773e793f39bf75,0xbf6f3e163f4abf6d,0x3f42bf713e2f3f46,
0x3f133edbbf7f3f0e,0xbf7e3f183ecfbf7f,0xbf803f043efcbf80,0x3ee6bf803f093ef1,0xbf7a3f2c3ea1bf7b,0x3e89bf783f313e95,0x3eb8bf7d3f1d3ec4,0x3f273eacbf7c3f22,
0x3f3ebf753e793f35,0x3e163f46bf713e48,0xbf673dc93f4ebf6d,0x3f5cbf623d493f55,0xbf803ef13f04bf80,0x3f18bf7f3edb3f0e,0x3eac3f22bf7d3ec4,0xbf783e953f2cbf7b,
0x3f2c3e95bf783f35,0xbf7d3f223eacbf7b,0x3edbbf7f3f183ec4,0x3f043ef1bf803f0e,0x3d49bf623f5c8000,0x3f4e3dc9bf673f55,0xbf713f463e16bf6d,0x3e79bf753f3e3e48,
0x3f65bf5c3cc93f55,0xbe603f71bf4abdc9,0x3e893f2cbf7c3ec4,0xbf6a3e163f42bf75,0xbf7f3f183eb8bf7b,0x3f13bf803efc3ef1,0x3dfbbf673f580000,0x3f313e79bf733f46,
0x3ee63f04bf803f0e,0xbf7a3eac3f1dbf7f,0xbf773f3e3e2fbf6d,0x3ecfbf7d3f273e95,0xbd97bf4e3f6fbe48,0x3f513d49bf5f3f62,0x3f7ebedbbf093f80,0xbf393f78bea1bf22,
0x3f7bbec4bf0e3f80,0xbf553f6dbe48bf35,0x3e48bf6d3f550000,0x3f0e3ec4bf7b3f35,0xbf7b3ec43f0ebf80,0x3f55bf6d3e483f35,0xbe483f6dbf550000,0xbf0ebec43f7bbf35,
0xbe483f6dbf558000,0xbf0ebec43f7bbf35,0x3f7bbec4bf0e3f80,0xbf553f6dbe48bf35,0x3e48bf6d3f558000,0x3f0e3ec4bf7b3f35,0xbf7b3ec43f0ebf80,0x3f55bf6d3e483f35,
0x3f65be16bf393f7b,0xbf7a3f3e3dfbbf62,0xbe893f71bf510000,0xbecfbf043f7fbf22,0xbf27be793f6fbf55,0x3f7cbedbbefc3f7f,0x3f1dbf803f093ec4,0x3cc93f4ebf733e95,
0xbee63f7dbf31be48,0xbe60bf2c3f7ebef1,0xbf773eac3f13bf80,0x3f6abf5c3d973f46,0x3f42bf783eb83f0e,0xbe2f3f67bf5f3dc9,0x3f4a3d49bf583f6d,0xbf803f183ea1bf75,
0x3edb3ef1bf7d3f35,0xbf5c3dc93f3ebf7b,0x3f80bf22be793f6d,0xbf4e3f75beacbf0e,0xbf713e953f18bf80,0x3f78bf46bd493f55,0xbf2c3f7fbf04bec4,0x3e16bf623f67be48,
0xbf673f62be16bf35,0x3f04bf7f3f2c3e48,0x3d493f46bf783ec4,0xbf18be953f71bf55,0x3eacbf753f4e8000,0x3e793f22bf803f0e,0xbf3ebdc93f5cbf6d,0x3f7dbef1bedb3f7b,
0xbf133f80bf27be48,0x3dfbbf5c3f6fbe95,0xbf803f183e89bf6d,0x3f65bf673e603f22,0xbf09beac3f73bf55,0x3f5fbe16bf313f7f,0x3ecfbf783f4a0000,0x3d973f3ebf7c3ef1,
0xbf513d493f42bf7b,0x3f7ebf04beb83f75,0x3cc9bf4e3f77bec4,0x3ee63edbbf7a3f46,0x3f58bf713ea13f0e,0xbefc3f7dbf39bdc9,0x3f6abe79bf1d3f80,0xbf7f3f2c3e2fbf62,
0x3f62be48bf223f80,0xbf7f3f0e3e95bf6d,0x3f75bf553dc93f35,0xbf463f7bbef1bec4,0x3ef1bf7b3f460000,0xbdc93f55bf753ec4,0xbe95bf0e3f7fbf35,0x3f223e48bf623f6d,
0xbef13f7bbf468000,0x3dc9bf553f75bec4,0x3e953f0ebf7f3f35,0xbf22be483f62bf6d,0x3f62be48bf223f80,0xbf7f3f0e3e95bf6d,0x3f75bf553dc93f35,0xbf463f7bbef1bec4,
0x3cc93f3ebf7e3f0e,0xbea1bf043f7cbf46,0xbf093f7dbf420000,0x3e89bf673f6abe95,0x3f6fbeacbefc3f7b,0xbf7f3f183e60bf62,0x3f133e79bf653f6d,0xbf4a3d493f39bf7f,
0xbf803f2c3dfbbf55,0x3f73bf5c3e2f3f22,0xbf583e163f27bf80,0x3f77bedbbecf3f75,0xbeb83f71bf5f3e48,0x3d97bf4e3f7abef1,0xbf513f78bee6bec4,0x3f1dbf803f313dc9,
0xbf7d3f46bd49bf35,0x3f71bf623e793f0e,0xbf5c3f75bedbbec4,0x3f3ebf7f3f183e48,0xbf4e3dc93f2cbf80,0x3f67be95bf043f7b,0xbf783ef13eacbf6d,0x3f80bf22be163f55,
0xbe16bf223f80bf35,0x3eac3ef1bf783f55,0xbf04be953f67bf6d,0x3f2c3dc9bf4e3f7b,0x3f18bf7f3f3e8000,0xbedb3f75bf5c3e48,0x3e79bf623f71bec4,0xbd493f46bf7d3f0e,
0x3dfbbf4e3f7cbf0e,0xbcc93f3ebf7f3f22,0x3ea1bf673f6fbec4,0xbe603f5cbf773ef1,0x3efcbf783f58be48,0xbecf3f71bf653e95,0x3f27bf803f390000,0xbf133f7dbf4a3dc9,
0x3f7ebf18be2f3f55,0xbf803f2c3d97bf46,0x3f73bedbbeb83f6d,0xbf7a3f043e89bf62,0x3f5fbe79bf093f7b,0xbf6a3eac3ee6bf75,0x3f42bd49bf313f80,0xbf513e163f1dbf7f,
0xbf8000003f80,0xbf8000003f80,0xbf8000003f80,0xbf8000003f80,0xbf8000003f80,0xbf8000003f80,0xbf8000003f80,0xbf8000003f80,
0x3f808000bf808000,0x3f808000bf808000,0x3f808000bf808000,0x3f808000bf808000,0x3f808000bf808000,0x3f808000bf808000,0x3f808000bf808000,0x3f808000bf808000,
0x3efc3f5cbf09bf55,0x3ecf3f67bee6bf62,0x3f273f3ebf31bf35,0x3f133f4ebf1dbf46,0x3dfb3f7dbe2fbf7b,0x3cc93f80bd97bf7f,0x3ea13f71beb8bf6d,0x3e603f78be89bf75,
0xbf5f3f043f58bf0e,0xbf6a3edb3f65bef1,0xbf423f2c3f39bf35,0xbf513f183f4abf22,0xbf7e3e163f7cbe48,0xbf803d493f7fbdc9,0xbf733eac3f6fbec4,0xbf7a3e793f77be95,
0xbf18bf463f2c3f35,0xbedbbf623f043f55,0xbe79bf753eac3f6d,0xbd49bf7f3e163f7b,0xbf7dbdc93f800000,0xbf71be953f783e48,0xbf5cbef13f673ec4,0xbf3ebf223f4e3f0e,
0x3f4ebf22bf3e3f35,0x3f67bef1bf5c3f0e,0x3f78be95bf713ec4,0x3f80bdc9bf7d3e48,0x3e16bf7fbd493f80,0x3eacbf75be793f7b,0x3f04bf62bedb3f6d,0x3f2cbf46bf183f55,
0x3eb83f67befcbf55,0x3d973f7dbe60bf75,0x3f513f04bf65bec4,0x3f1d3f3ebf39bf22,0x3f80bd49bf7e3e48,0x3f733e79bf7cbdc9,0x3f58bf18bf423f35,0x3f77beacbf6a3ef1,
0xbf6f3edb3f5fbf0e,0xbf7f3e163f7abe95,0xbf133f5c3ee6bf6d,0xbf4a3f2c3f31bf46,0xbcc93f80bdfbbf7b,0xbea13f783e2fbf7f,0x3f093f4ebf27bf35,0x3e893f71becfbf62,
0xbe953f7b3dc9bf80,0xbf223f553ef1bf6d,0xbf623f0e3f46bf35,0xbf7f3e483f75bec4,0xbf75be483f7f0000,0xbf46bf0e3f623ec4,0xbef1bf553f223f35,0xbdc9bf7b3e953f6d,
0xbf75be483f7f8000,0xbf46bf0e3f623ec4,0xbef1bf553f223f35,0xbdc9bf7b3e953f6d,0x3e95bf7bbdc93f80,0x3f22bf55bef13f6d,0x3f62bf0ebf463f35,0x3f7fbe48bf753ec4,
0x3f09bf67bea13f7b,0x3f5fbf18bf393f46,0xbecfbf5c3f1d3f35,0x3d97bf803e2f3f75,0x3f133f3ebf42bf0e,0x3dfb3f78beb8bf62,0x3f80be16bf773ec4,0x3f653eacbf7abdc9,
0x3f583edbbf73be48,0x3efc3f4ebf31bf22,0x3f6abf04bf4a3f35,0x3f7fbd49bf7c3e95,0xbf513f2c3f27bf55,0xbf7e3e793f6fbef1,0x3cc93f7dbe89bf6d,0xbee63f713e60bf7f,
0xbf713ef13f4ebf35,0xbf78bdc93f80be48,0xbf2cbf223f5c3ec4,0xbe16bf753edb3f55,0x3f673e95bf7d0000,0x3f043f46bf3ebf0e,0xbd493f7fbe79bf6d,0xbf183f623eacbf7b,
0xbeacbf623f183f35,0x3e79bf7f3d493f7b,0x3f3ebf46bf043f6d,0x3f7dbe95bf673f0e,0xbedb3f753e16bf80,0xbf5c3f223f2cbf55,0xbf803dc93f78bec4,0xbf4ebef13f713e48,
0x3f423f04bf6fbe48,0x3e2f3f71befcbf46,0x3f4abf3ebf093f6d,0x3f80be16bf733ef1,0xbee6bf4e3f393f0e,0x3e60bf803dfb3f75,0xbf773edb3f51bf35,0xbf6abe793f7fbdc9,
0xbf273f5c3eb8bf7b,0xbf7c3eac3f5fbf22,0x3f1d3f2cbf58bec4,0xbcc93f7dbea1bf62,0x3f65bf18bf313f55,0x3f7a3d49bf7e3e95,0xbe89bf673f133f35,0x3ecfbf78bd973f7f,
0x3f0ebf6dbe483f80,0x3f7bbec4bf553f35,0x3f553ec4bf7b0000,0x3e483f6dbf0ebf35,0xbf0e3f6d3e48bf80,0xbf7b3ec43f55bf35,0xbf55bec43f7b0000,0xbe48bf6d3f0e3f35,
0x3f553ec4bf7b8000,0x3e483f6dbf0ebf35,0xbf0e3f6d3e48bf80,0xbf7b3ec43f55bf35,0xbf55bec43f7b8000,0xbe48bf6d3f0e3f35,0x3f0ebf6dbe483f80,0x3f7bbec4bf553f35,
0xbf7f3e163f6fbf0e,0xbf13bf2c3f5f3e95,0x3dfb3f71bf09bf35,0xbf313f5c3ea1bf7f,0x3f653e79bf803e48,0x3e603f67bf1dbf22,0x3e89bf803e2f3f6d,0x3f6abf18bf273f62,
0x3d97bf7d3eb83f55,0x3f51bf3ebefc3f75,0xbf7e3eac3f58bf35,0xbf39bf043f733dc9,0xbee63f783cc9bf7b,0xbf7a3edb3f4abf46,0x3f773d49bf7c3ec4,0x3ecf3f4ebf42bef1,
0x3d493f75bf04bf35,0xbf4e3f463edbbf7b,0xbf71bdc93f7dbec4,0xbe79bf623f2c3f0e,0xbf3ebef13f780000,0x3e16bf7f3eac3f55,0x3f67bf22bf183f6d,0x3f5c3e95bf803e48,
0xbf803e953f5cbf35,0xbf18bf223f673e48,0x3eacbf7f3e163f6d,0x3f78bef1bf3e3f55,0x3f2cbf62be793f80,0x3f7dbdc9bf713f0e,0x3edb3f46bf4ebec4,0xbf043f753d49bf7b,
0x3f7abd49bf733f0e,0x3e893f5cbf39bef1,0xbeb8bf4e3f4a3ec4,0x3f27bf67be2f3f7f,0xbf133f713d97bf7b,0xbf7e3e163f6abf22,0x3f80be79bf5f3f35,0x3ee63f3ebf58be95,
0xbe603f80bea1bf55,0xbf773f043f31bf62,0x3f6fbf18bf1d3f6d,0x3f423edbbf7c3dc9,0xbf51beac3f7fbe48,0x3dfbbf7d3ecf3f46,0xbcc93f78befcbf35,0xbf653f2c3f09bf75,
0xbf463f553e95bf80,0xbf62be483f7fbec4,0x3dc9bf7b3ef13f35,0x3f75bf0ebf223f6d,0x3f223f0ebf750000,0xbef13f7bbdc9bf6d,0xbf7f3e483f62bf35,0xbe95bf553f463ec4,
0xbf22bf0e3f758000,0x3ef1bf7b3dc93f6d,0x3f7fbe48bf623f35,0x3e953f55bf46bec4,0xbf463f553e95bf80,0xbf62be483f7fbec4,0x3dc9bf7b3ef13f35,0x3f75bf0ebf223f6d,
0x3ecf3f3ebf5fbe48,0xbf423f5c3e60bf7f,0x3e2fbf7d3ee63f35,0x3f7ebedbbf393f62,0x3f80beacbf4a3f55,0x3ea13f4ebf51be95,0xbf58be793f7fbec4,0x3e89bf803eb83f46,
0xbf6a3f2c3efcbf7b,0xbf27bf043f7abdc9,0x3f7cbe16bf653f35,0x3dfb3f67bf31bef1,0x3cc93f71bf1dbf0e,0xbf733f183f13bf75,0x3f09bf783d973f6d,0x3f77bd49bf6f3f22,
0x3f78bdc9bf673f35,0xbd493f75bf18bf0e,0xbf7d3ef13f2cbf6d,0xbeacbf463f5c3e48,0x3f043f22bf710000,0xbf3e3f623e16bf7b,0xbf4ebe953f80bec4,0x3edbbf7f3e793f55,
0xbe793f7fbedbbf35,0xbf803e953f4ebf55,0xbe16bf623f3e3ec4,0x3f71bf22bf043f7b,0xbf5c3f463eacbf80,0xbf2cbef13f7dbe48,0x3f18bf753d493f6d,0x3f673dc9bf783f0e,
0x3f77bf18bf093f7b,0x3eb83f3ebf65bdc9,0xbf7f3edb3f31bf6d,0xbe2fbf5c3f4a3e95,0x3f7ebe79bf513f55,0xbcc93f71bf27bef1,0xbf733d493f6abf35,0x3e60bf7d3efc3f22,
0x3e893f4ebf58be48,0xbf6f3f2c3ee6bf7f,0xbd97bf673f393ec4,0x3f7cbf04bf1d3f75,0xbdfb3f78bf13bf0e,0xbf803eac3f42bf62,0x3ea1bf803ecf3f35,0x3f7abe16bf5f3f46,
0x3f6dbf35bec43f80,0x3ec43f35bf6d0000,0xbf6d3f353ec4bf80,0xbec4bf353f6d0000,0x3f6dbf35bec43f80,0x3ec43f35bf6d0000,0xbf6d3f353ec4bf80,0xbec4bf353f6d0000,
0x3ec43f35bf6d8000,0xbf6d3f353ec4bf80,0xbec4bf353f6d8000,0x3f6dbf35bec43f80,0x3ec43f35bf6d8000,0xbf6d3f353ec4bf80,0xbec4bf353f6d8000,0x3f6dbf35bec43f80,
0x3f1dbf783e2f3f55,0x3f393eacbf7f3ef1,0xbee63f80beb8bf35,0xbf58be163f77bf22,0x3f5fbf4ebe603f7b,0x3ecf3f2cbf733dc9,0xbf423f673cc9bf6d,0xbf13bf043f7ebe95,
0x3f4a3e79bf7c3f0e,0xbf313f71bd97bf62,0xbf65bd493f6fbf35,0x3f09bf7d3e893f46,0x3efc3f18bf7a3e48,0xbf6a3f3e3ea1bf7f,0xbf27bedb3f80bec4,0x3f51bf5cbdfb3f75,
0x3f04bf7f3eac3f35,0x3f3e3e95bf7d3f0e,0xbf4e3f623d49bf6d,0xbedbbf223f78be48,0xbe79bf463f670000,0x3f80bef1bf183f7b,0xbe163f75bf2cbec4,0xbf713dc93f5cbf55,
0x3f5c3dc9bf713f35,0xbf2c3f75be16bf55,0xbf18bef13f80bec4,0x3f67bf46be793f7b,0x3f78bf22bedb3f80,0x3d493f62bf4ebe48,0xbf7d3e953f3ebf6d,0x3eacbf7f3f043f0e,
0x3f39bf713dfb3f55,0x3ee63f18bf7c3e95,0xbe603f78bf27bec4,0xbf5fbd493f6abf46,0xbeb8bf2c3f77be48,0x3f7fbf04bf093f7f,0x3f513e16bf733f35,0xbf4a3f67bcc9bf62,
0x3f313eacbf7e3f0e,0xbf653f4e3e2fbf75,0xbf7a3e793f42bf6d,0x3efcbf803ecf3f22,0x3f6fbf3ebe893f7b,0x3d973f5cbf58bdc9,0xbf133f7dbea1bf35,0xbf1dbedb3f80bef1,
0xbf7f3f0e3ef1bf80,0x3e95bf7b3f223ec4,0x3f463e48bf753f35,0xbf623f553dc9bf6d,0xbdc9bf553f620000,0x3f75be48bf463f6d,0xbf223f7bbe95bf35,0xbef1bf0e3f7fbec4,
0xbdc9bf553f628000,0x3f75be48bf463f6d,0xbf223f7bbe95bf35,0xbef1bf0e3f7fbec4,0x3f7fbf0ebef13f80,0xbe953f7bbf22bec4,0xbf46be483f75bf35,0x3f62bf55bdc93f6d,
0xbf7c3eac3f27bf7b,0x3f1dbf7d3eb83f22,0x3f31bf783e893f35,0x3ea13f2cbf7a3e95,0x3f09bf803ee63f0e,0x3efc3f04bf803ef1,0x3ecf3f18bf7e3ec4,0xbf7f3edb3f13bf7f,
0x3e2fbf713f423e48,0x3f4a3e16bf6f3f46,0x3f393e79bf773f35,0xbf733f3e3e60bf75,0x3f583d49bf653f55,0xbf5f3f5c3cc9bf62,0xbf6a3f4e3dfbbf6d,0x3d97bf673f513dc9,
0xbf2cbe953f78bf35,0x3f7dbf22beac3f7b,0xbedb3f7fbf18bec4,0xbf04bef13f80bf0e,0xbd493f62bf5c0000,0xbf4ebdc93f67bf55,0x3f71bf46be163f6d,0xbe793f75bf3ebe48,
0x3f3ebf753e793f35,0x3e163f46bf713e48,0xbf673dc93f4ebf6d,0x3f5cbf623d493f55,0xbf803ef13f04bf80,0x3f18bf7f3edb3f0e,0x3eac3f22bf7d3ec4,0xbf783e953f2cbf7b,
0x3ea1bf783f393e48,0x3f093edbbf7e3f22,0x3f5fbd49bf513f6d,0xbf6f3f4e3d97bf62,0xbf273f7dbecfbf0e,0xbe2fbf3e3f77be95,0xbf1dbeac3f7abf35,0x3f80bf04bee63f7f,
0x3f73be79bf313f7b,0xbf583f67bdfbbf46,0xbefc3f80bf13bec4,0xbeb8bf183f7fbef1,0xbf42be163f6abf55,0x3f7cbf2cbe893f75,0x3f4abf713e603f35,0xbcc93f5cbf653dc9,
0x3f7bbec4bf0e3f80,0xbf553f6dbe48bf35,0x3e48bf6d3f550000,0x3f0e3ec4bf7b3f35,0xbf7b3ec43f0ebf80,0x3f55bf6d3e483f35,0xbe483f6dbf550000,0xbf0ebec43f7bbf35,
0xbe483f6dbf558000,0xbf0ebec43f7bbf35,0x3f7bbec4bf0e3f80,0xbf553f6dbe48bf35,0x3e48bf6d3f558000,0x3f0e3ec4bf7b3f35,0xbf7b3ec43f0ebf80,0x3f55bf6d3e483f35,
0x3ea13f18bf803f0e,0xbf583d493f4abf75,0xbf5f3f67be2fbf35,0x3eb8bf783f423dc9,0x3d97bf5c3f6abe48,0x3f133eacbf773f46,0x3f7ebf2cbe603f6d,0xbf313f7dbee6bef1,
0xbf733f4e3cc9bf55,0x3f09bf803f1d3e95,0xbefcbedb3f7cbf35,0x3f6fbe79bf273f7f,0x3f7fbf04becf3f7b,0xbf513f71be89bf22,0x3dfb3f3ebf7a3ec4,0xbf39be163f65bf62,
0xbf673f62be16bf35,0x3f04bf7f3f2c3e48,0x3d493f46bf783ec4,0xbf18be953f71bf55,0x3eacbf753f4e0000,0x3e793f22bf803f0e,0xbf3ebdc93f5cbf6d,0x3f7dbef1bedb3f7b,
0xbedbbef13f7dbf35,0x3f5cbdc9bf3e3f7b,0xbf803f223e79bf6d,0x3f4ebf753eac3f0e,0x3f71be95bf183f80,0xbf783f463d49bf55,0x3f2cbf7f3f043ec4,0xbe163f62bf673e48,
0xbe2fbf2c3f7fbf0e,0x3f1d3e79bf6a3f62,0x3f39bf7d3efc3ec4,0xbea13f71bf583dc9,0x3f7abedbbee63f7b,0xbf773f4ebcc9bf46,0x3eb83f04bf7e3f35,0xbf42bd493f51bf75,
0x3f7cbf3ebd973f55,0xbf4a3f78becfbef1,0x3f313e16bf5f3f6d,0xbf733eac3f09bf7f,0xbe603f67bf653e48,0xbe89bf183f80bf22,0xbf6f3f5cbdfbbf35,0x3f27bf803f133e95,
0xbf623e483f22bf80,0x3f7fbf0ebe953f6d,0xbf753f55bdc9bf35,0x3f46bf7b3ef13ec4,0xbef13f7bbf460000,0x3dc9bf553f75bec4,0x3e953f0ebf7f3f35,0xbf22be483f62bf6d,
0x3ef1bf7b3f468000,0xbdc93f55bf753ec4,0xbe95bf0e3f7fbf35,0x3f223e48bf623f6d,0xbf623e483f22bf80,0x3f7fbf0ebe953f6d,0xbf753f55bdc9bf35,0x3f46bf7b3ef13ec4,
0x3f31bf803f1d3e48,0xbee63f78bf513dc9,0x3f7abf4e3d973f35,0xbf5f3f71beb8bef1,0xbecfbedb3f77bf55,0x3f273e16bf583f75,0x3e2fbf5c3f73bec4,0x3dfb3f2cbf803f22,
0x3f393d49bf4a3f7b,0xbf653e793f13bf7f,0x3e603f18bf7f3f35,0xbefcbeac3f6fbf62,0x3f6abf673e893f0e,0xbf423f7dbf09be95,0x3f7cbf04bea13f6d,0xbf7e3f3e3cc9bf46,
0x3e163f22bf803f35,0xbeacbef13f78bf55,0x3f043e95bf673f6d,0xbf2cbdc93f4ebf7b,0xbf183f7fbf3e0000,0x3edbbf753f5cbe48,0xbe793f62bf713ec4,0x3d49bf463f7dbf0e,
0xbf7d3f46bd49bf35,0x3f71bf623e793f0e,0xbf5c3f75bedbbec4,0x3f3ebf7f3f183e48,0xbf4e3dc93f2cbf80,0x3f67be95bf043f7b,0xbf783ef13eacbf6d,0x3f80bf22be163f55,
0xbf1dbe163f51bf7b,0x3f313d49bf423f7f,0xbee6beac3f6abf6d,0x3f093e79bf5f3f75,0xbe89bf043f7abf55,0x3eb83edbbf733f62,0xbd97bf2c3f80bf35,0x3e2f3f18bf7e3f46,
0x3f4abf7d3f133e48,0xbf393f80bf27bdc9,0x3f65bf713ecf3ec4,0xbf583f78befcbe95,0x3f77bf5c3e603f0e,0xbf6f3f67bea1bef1,0x3f7fbf3e3cc93f35,0xbf7c3f4ebdfbbf22,
0xbf3500003f353f80,0x3f350000bf35bf80,0xbf3500003f353f80,0x3f350000bf35bf80,0xbf3500003f353f80,0x3f350000bf35bf80,0xbf3500003f353f80,0x3f350000bf35bf80,
0xbf35bf80bf358000,0x3f353f803f358000,0xbf35bf80bf358000,0x3f353f803f358000,0xbf35bf80bf358000,0x3f353f803f358000,0xbf35bf80bf358000,0x3f353f803f358000,
0x3e89be793e60be48,0x3eb8beac3ea1be95,0x3d97bd493cc90000,0x3e2fbe163dfbbdc9,0x3f1dbf183f13bf0e,0x3f31bf2c3f27bf22,0x3ee6bedb3ecfbec4,0x3f09bf043efcbef1,
0x3f77bf783f7abf7b,0x3f6fbf713f73bf75,0x3f7fbf803f80bf80,0x3f7cbf7d3f7ebf7f,0x3f4abf4e3f51bf55,0x3f39bf3e3f42bf46,0x3f65bf673f6abf6d,0x3f58bf5c3f5fbf62,
0x3f18bf223f2cbf35,0x3edbbef13f04bf0e,0x3e79be953eacbec4,0x3d49bdc93e16be48,0x3f7dbf7f3f80bf80,0x3f71bf753f78bf7b,0x3f5cbf623f67bf6d,0x3f3ebf463f4ebf55,
0xbf4e3f46bf3e3f35,0xbf673f62bf5c3f55,0xbf783f75bf713f6d,0xbf803f7fbf7d3f7b,0xbe163dc9bd498000,0xbeac3e95be793e48,0xbf043ef1bedb3ec4,0xbf2c3f22bf183f0e,
0xbf6a3f71bf773f7b,0xbf423f4ebf583f62,0xbf7c3f78bf733f6d,0xbf7e3f80bf803f7f,0xbf393f2cbf1d3f0e,0xbf653f5cbf513f46,0xbe603e16bd970000,0xbefc3edbbeb83e95,
0x3ecfbeac3e89be48,0x3f27bf183f09bef1,0xbe2f3e79bea13ec4,0x3dfbbd49bcc93dc9,0xbf313f3ebf4a3f55,0xbee63f04bf133f22,0xbf7a3f7dbf7f3f80,0xbf5f3f67bf6f3f75,
0xbf753f7bbf7f3f80,0xbf463f55bf623f6d,0xbef13f0ebf223f35,0xbdc93e48be953ec4,0x3e95be483dc90000,0x3f22bf0e3ef1bec4,0x3f62bf553f46bf35,0x3f7fbf7b3f75bf6d,
0x3e95be483dc98000,0x3f22bf0e3ef1bec4,0x3f62bf553f46bf35,0x3f7fbf7b3f75bf6d,0x3f75bf7b3f7fbf80,0x3f46bf553f62bf6d,0x3ef1bf0e3f22bf35,0x3dc9be483e95bec4,
0x3f7abf713f65bf55,0x3f77bf7d3f80bf7f,0x3eb8be793dfb0000,0x3f42bf2c3f13bef1,0xbe2f3d493d97be48,0xbf1d3f04becf3e95,0x3f39bf4e3f5fbf6d,0x3ea1bedb3f09bf22,
0x3e60beac3ee6bf0e,0xbe893e16bcc9bdc9,0x3f6fbf783f7ebf80,0x3f27bf3e3f51bf62,0xbf7c3f80bf7f3f7b,0xbf4a3f5cbf6a3f75,0xbf313f18befc3ec4,0xbf733f67bf583f46,
0xbf713f62bf4e3f35,0xbf783f7fbf803f7b,0xbf2c3f46bf5c3f6d,0xbe163e95bedb3f0e,0x3f67bf753f7dbf80,0x3f04bf223f3ebf55,0xbd49bdc93e79bec4,0xbf183ef1beac3e48,
0xbeac3ef1bf183f35,0x3e79bdc9bd493e48,0x3f3ebf223f04bec4,0x3f7dbf753f67bf55,0xbedb3e95be168000,0xbf5c3f46bf2c3f0e,0xbf803f7fbf783f6d,0xbf4e3f62bf713f7b,
0x3f7fbf783f6abf55,0x3f51bf673f77bf7f,0x3dfb3d49be603ec4,0x3f39bf183ee6be95,0xbf733f7dbf803f7b,0xbf093f2cbf4a3f62,0xbefc3eacbe2f0000,0xbf6f3f5cbf423f22,
0x3d97be793ecfbf0e,0xbf133edbbe893dc9,0x3f7ebf803f7abf6d,0x3f31bf4e3f65bf75,0x3ea1be16bcc93e48,0x3f58bf3e3f1dbef1,0xbf5f3f71bf7c3f80,0xbeb83f04bf273f46,
0xbf553f6dbf7b3f80,0xbe483ec4bf0e3f35,0x3f0ebec43e480000,0x3f7bbf6d3f55bf35,0x3f55bf6d3f7bbf80,0x3e48bec43f0ebf35,0xbf0e3ec4be480000,0xbf7b3f6dbf553f35,
0x3f0ebec43e488000,0x3f7bbf6d3f55bf35,0x3f55bf6d3f7bbf80,0x3e48bec43f0ebf35,0xbf0e3ec4be488000,0xbf7b3f6dbf553f35,0xbf553f6dbf7b3f80,0xbe483ec4bf0e3f35,
0x3f27bf4e3f6abf7b,0xbe2fbd493e89bef1,0x3f1dbedb3e600000,0x3f80bf783f65bf46,0xbea13f04bf313f55,0x3f09beac3dfb3dc9,0xbf5f3f3ebf133ec4,0xbf6f3f7dbf7f3f75,
0xbf423f18becf3e48,0xbf7c3f80bf773f62,0x3f4abf673f7abf80,0x3cc9be793ee6bf22,0x3f73bf5c3f39bf0e,0x3f58bf713f7ebf7f,0xbefc3f2cbf513f6d,0x3eb8be16bd973e95,
0xbd493e95bf043f35,0x3f4ebf223edbbe48,0x3f71bf7f3f7dbf6d,0x3e79bef13f2cbf55,0x3f3ebf623f78bf80,0xbe16bdc93eacbf0e,0xbf673f46bf183ec4,0xbf5c3f75bf803f7b,
0x3f80bf753f5cbf35,0x3f18bf463f67bf7b,0xbeac3dc93e16bec4,0xbf783f62bf3e3f0e,0xbf2c3ef1be798000,0xbf7d3f7fbf713f55,0xbedb3f22bf4e3f6d,0x3f04be953d493e48,
0xbf583f2cbee63e48,0xbf5f3f78bf803f75,0x3f6abf7d3f7ebf6d,0x3d97beac3f13bf46,0xbe2f3edbbf273f55,0x3f4abf183eb8bdc9,0xbf393f04be890000,0xbf733f80bf7a3f62,
0xbf093f3ebf653f7b,0x3efcbe79bcc93e95,0xbecf3e163dfbbec4,0xbf7f3f71bf513f22,0x3f7cbf673f42bf0e,0x3f1dbf4e3f6fbf7f,0xbf313f5cbf773f80,0x3ea1bd49be603ef1,
0xbf223f55bf753f80,0x3ef1be48bdc93ec4,0x3f7fbf7b3f62bf35,0x3e95bf0e3f46bf6d,0xbf463f0ebe950000,0xbf623f7bbf7f3f6d,0x3dc93e48bef13f35,0x3f75bf553f22bec4,
0x3f46bf0e3e958000,0x3f62bf7b3f7fbf6d,0xbdc9be483ef1bf35,0xbf753f55bf223ec4,0xbf223f55bf753f80,0x3ef1be48bdc93ec4,0x3f7fbf7b3f62bf35,0x3e95bf0e3f46bf6d,
0xbeb83d493e89bf0e,0xbf7f3f78bf583f22,0x3f51bf183ea10000,0x3f4abf713f80bf75,0x3f39bf673f7ebf7b,0xbee63e163e2fbef1,0xbe603f04bf423f6d,0x3f5fbf2c3ecfbdc9,
0xbf6f3f80bf773f55,0x3d973e79bf093f46,0x3f13bf4e3f73bf80,0xbf1d3eacbcc9be95,0xbf313edbbdfbbe48,0xbf653f7dbf7c3f62,0x3f7abf5c3f27bec4,0x3efcbf3e3f6abf7f,
0x3f78bf7f3f67bf35,0xbd49be953f18bf55,0xbf7d3f62bf2c3ec4,0xbeac3f22bf5c3f7b,0x3f04bf463f71bf80,0xbf3e3ef1be16be48,0xbf4e3f75bf803f6d,0x3edbbdc9be793f0e,
0xbe79bdc93edbbf35,0xbf803f75bf4e3f0e,0xbe163ef1bf3e3f6d,0x3f71bf463f04be48,0xbf5c3f22beac8000,0xbf2c3f62bf7d3f7b,0x3f18be95bd493ec4,0x3f67bf7f3f78bf55,
0x3efcbe16be603f0e,0x3f6abf803f73bf46,0xbf273eac3cc9bec4,0xbf513f78bf7e3f62,0x3f4abf043e2f3e48,0x3f31bf673f7fbf75,0xbf653f2cbeb80000,0xbf093f4ebf773f7f,
0x3f5fbf7d3f7abf55,0xbecf3d493ea1bf22,0xbf423f71bf803f6d,0x3f13be79bdfb3ef1,0x3f1dbf5c3f7cbf7b,0xbf393edbbd97be95,0xbee63f3ebf6f3f80,0x3f58bf183e893dc9,
0xbec43f35bf6d3f80,0x3f6dbf353ec40000,0x3ec4bf353f6dbf80,0xbf6d3f35bec40000,0xbec43f35bf6d3f80,0x3f6dbf353ec40000,0x3ec4bf353f6dbf80,0xbf6d3f35bec40000,
0x3f6dbf353ec48000,0x3ec4bf353f6dbf80,0xbf6d3f35bec48000,0xbec43f35bf6d3f80,0x3f6dbf353ec48000,0x3ec4bf353f6dbf80,0xbf6d3f35bec48000,0xbec43f35bf6d3f80,
0xbf7e3f5cbf133e48,0xbcc93edbbf423f75,0x3f73bf3e3ecf0000,0x3e60bf183f5fbf7f,0xbf773f7dbf583f0e,0x3eb83d49bee63f46,0x3f7fbf713f39bec4,0xbe2fbe793f1dbf62,
0xbdfb3f04bf513f7b,0x3f80bf673f27be95,0x3ea1bf2c3f6abf80,0xbf7a3f4ebefc3dc9,0x3e893e16bf093f55,0x3f6fbf803f65bf22,0xbd97beac3f31bf6d,0xbf7c3f78bf4a3ef1,
0xbf043dc93eacbf35,0xbf3e3f75bf7d3f55,0x3f4ebef13d493ec4,0x3edbbf463f78bf7b,0x3e79bf223f67bf80,0xbf803f62bf183e48,0x3e163e95bf2c3f6d,0x3f71bf7f3f5cbf0e,
0xbf5c3f7fbf713f35,0x3f2cbe95be163f0e,0x3f18bf623f80bf6d,0xbf673f22be79be48,0xbf783f46bedb8000,0xbd493ef1bf4e3f7b,0x3f7dbf753f3ebec4,0xbeacbdc93f04bf55,
0xbcc9bedb3f4abf7b,0xbf733f7dbf513ef1,0xbf093f5cbf7f3f6d,0x3f77bf3e3eb83dc9,0x3f6abf803f5fbf0e,0xbf273e793e60bf22,0xbf7c3f4ebee60000,0x3dfb3eacbf393f75,
0xbf803f67bf1d3e48,0x3ea13e16bf133f62,0x3f58bf043d973ec4,0x3e89bf2c3f6fbf7f,0xbecfbd493efcbf55,0xbf423f78bf7a3f46,0xbe2f3f18bf653f80,0x3f7ebf713f31be95,
0xbdc93f0ebf623f80,0x3f75bf7b3f46bec4,0xbf223e483e95bf35,0xbef13f55bf7f3f6d,0x3f7fbf553ef10000,0xbe95be483f22bf6d,0xbf463f7bbf753f35,0x3f62bf0e3dc93ec4,
0x3f7fbf553ef18000,0xbe95be483f22bf6d,0xbf463f7bbf753f35,0x3f62bf0e3dc93ec4,0x3dc9bf0e3f62bf80,0xbf753f7bbf463ec4,0x3f22be48be953f35,0x3ef1bf553f7fbf6d,
0xbf133f67bf7f3f55,0x3f7ebf4e3ecf3dc9,0x3f80bf5c3efc0000,0xbee6bd493f09bf62,0x3f7abf3e3ea13e48,0xbe89be793f31bf75,0xbeb8be163f1dbf6d,0xbf273f71bf7c3f46,
0x3f51bedbbd973f0e,0x3dfbbf183f6abf7f,0x3cc9bf043f5fbf80,0xbf653f80bf583ef1,0x3e60bf2c3f73bf7b,0xbf773f78bf393e95,0xbf6f3f7dbf4a3ec4,0x3f42beacbe2f3f22,
0xbf2c3f75bf783f35,0x3f7dbf463eac3e48,0xbedbbdc93f18bf6d,0xbf043f62bf803f55,0xbd49bef13f5cbf80,0xbf4e3f7fbf673f0e,0x3f71bf223e163ec4,0xbe79be953f3ebf7b,
0x3f3ebe95be793f35,0x3e16bf223f71bf7b,0xbf673f7fbf4e3ec4,0x3f5cbef1bd493f0e,0xbf803f62bf048000,0x3f18bdc9bedb3f55,0x3eacbf463f7dbf6d,0xbf783f75bf2c3e48,
0xbee63f5cbf803f55,0x3f7abf713f1dbdc9,0x3f77bf2c3e2f3ec4,0xbecfbe163f27bf75,0x3d97bf183f6fbf7b,0xbf513f80bf5f3ef1,0xbf7e3f67bf090000,0x3f39be79bea13f46,
0x3f65bf04bcc93f0e,0xbe60beac3f4abf7f,0x3e89bf3e3f7cbf6d,0xbf6a3f7dbf423e95,0xbf7f3f4ebeb8be48,0x3f13bd49befc3f62,0x3dfb3edbbf583f80,0x3f31bf783f73bf22,
0x3e483ec4bf553f80,0x3f0ebf6d3f7bbf35,0xbf7b3f6dbf0e0000,0x3f55bec4be483f35,0xbe48bec43f55bf80,0xbf0e3f6dbf7b3f35,0x3f7bbf6d3f0e0000,0xbf553ec43e48bf35,
0x3f7bbf6d3f0e8000,0xbf553ec43e48bf35,0x3e483ec4bf553f80,0x3f0ebf6d3f7bbf35,0xbf7b3f6dbf0e8000,0x3f55bec4be483f35,0xbe48bec43f55bf80,0xbf0e3f6dbf7b3f35,
0x3ee63e16bf313f7b,0x3e60bf3e3f7ebf62,0x3f77bf713f130000,0xbf6a3f043d97bf22,0xbf423e793eb8bf55,0x3e2f3edbbf5f3f7f,0xbf4a3f80bf583ec4,0x3f80bf4e3ea13e95,
0x3f65bf7d3f39be48,0xbf7a3f2cbdfbbef1,0xbe89beac3f51bf80,0xbecf3f5cbf7f3f46,0xbf273f78bf6f3f0e,0x3f7cbf673efc3dc9,0x3f1dbd49bf093f6d,0x3cc9bf183f73bf75,
0x3f67bef1be163f35,0xbf04bdc93f2cbf7b,0xbd493f22bf783f6d,0x3f18bf753f71bf0e,0xbeacbe953f4ebf80,0xbe793f46bf803f55,0x3f3ebf7f3f5cbec4,0xbf7d3f62bedbbe48,
0x3edbbf623f7dbf35,0xbf5c3f7fbf3e3e48,0x3f80bf463e793ec4,0xbf4e3e953eacbf55,0xbf713f75bf188000,0x3f78bf223d493f0e,0xbf2c3dc93f04bf6d,0x3e163ef1bf673f7b,
0x3f51bf803f42be48,0xbf7e3f5cbeb8be95,0xbcc9bf183f77bf6d,0xbee63f67bf7a3f22,0xbf583eac3ea1bf55,0x3efc3e16bf393f7f,0xbf6a3f78bf1d0000,0x3f7fbf3e3e2f3ef1,
0xbf13bd493f27bf7b,0x3dfb3f04bf6f3f75,0xbf803f4ebe89bec4,0x3f65bedbbe603f46,0xbf093f71bf733f0e,0x3f5fbf7d3f31bdc9,0x3ecf3e79bf4a3f80,0x3d97bf2c3f7cbf62,
0x3ef13e48bf463f80,0xbdc9bf0e3f75bf6d,0xbe953f55bf7f3f35,0x3f22bf7b3f62bec4,0xbf623f7bbf220000,0x3f7fbf553e953ec4,0xbf753f0e3dc9bf35,0x3f46be48bef13f6d,
0x3f62bf7b3f228000,0xbf7f3f55be95bec4,0x3f75bf0ebdc93f35,0xbf463e483ef1bf6d,0x3ef13e48bf463f80,0xbdc9bf0e3f75bf6d,0xbe953f55bf7f3f35,0x3f22bf7b3f62bec4,
0x3f80bf3e3dfb3f0e,0xbf733f043e2fbf46,0x3f58bf7d3f270000,0xbf773f67becfbe95,0x3eb83eacbf5f3f7b,0xbd97bf183f7abf62,0x3f51be79bee63f6d,0xbf1dbd493f31bf7f,
0x3cc9bf2c3f7ebf55,0xbea13f5cbf7c3f22,0xbf09be163f42bf80,0x3e893edbbf6a3f75,0x3f6fbf713efc3e48,0xbf7f3f4ebe60bef1,0x3f13bf783f65bec4,0xbf4a3f80bf393dc9,
0x3e16bf463f80bf35,0xbeac3f62bf783f0e,0x3f04bf753f67bec4,0xbf2c3f7fbf4e3e48,0xbf18bdc93f3ebf80,0x3edb3e95bf5c3f7b,0xbe79bef13f71bf6d,0x3d493f22bf7d3f55,
0xbf7d3f223d49bf35,0x3f71bef1be793f55,0xbf5c3e953edbbf6d,0x3f3ebdc9bf183f7b,0xbf4e3f7fbf2c8000,0x3f67bf753f043e48,0xbf783f62beacbec4,0x3f80bf463e163f0e,
0xbf7e3f4ebe2fbf0e,0x3f80bf3e3d973f22,0xbf733f67beb8bec4,0x3f7abf5c3e893ef1,0xbf5f3f78bf09be48,0x3f6abf713ee63e95,0xbf423f80bf310000,0x3f51bf7d3f1d3dc9,
0x3dfb3f18bf7c3f55,0xbcc9bf2c3f7fbf46,0x3ea13edbbf6f3f6d,0xbe60bf043f77bf62,0x3efc3e79bf583f7b,0xbecfbeac3f65bf75,0x3f273d49bf393f80,0xbf13be163f4abf7f,
0xbf3500003f353f80,0x3f350000bf35bf80,0xbf3500003f353f80,0x3f350000bf35bf80,0xbf3500003f353f80,0x3f350000bf35bf80,0xbf3500003f353f80,0x3f350000bf35bf80,
0xbf35bf80bf358000,0x3f353f803f358000,0xbf35bf80bf358000,0x3f353f803f358000,0xbf35bf80bf358000,0x3f353f803f358000,0xbf35bf80bf358000,0x3f353f803f358000,
0x3f5fbf5c3f58bf55,0x3f6abf673f65bf62,0x3f42bf3e3f39bf35,0x3f51bf4e3f4abf46,0x3f7ebf7d3f7cbf7b,0x3f80bf803f7fbf7f,0x3f73bf713f6fbf6d,0x3f7abf783f77bf75,
0x3efcbf043f09bf0e,0x3ecfbedb3ee6bef1,0x3f27bf2c3f31bf35,0x3f13bf183f1dbf22,0x3dfbbe163e2fbe48,0x3cc9bd493d97bdc9,0x3ea1beac3eb8bec4,0x3e60be793e89be95,
0xbf4e3f46bf3e3f35,0xbf673f62bf5c3f55,0xbf783f75bf713f6d,0xbf803f7fbf7d3f7b,0xbe163dc9bd490000,0xbeac3e95be793e48,0xbf043ef1bedb3ec4,0xbf2c3f22bf183f0e,
0xbf183f22bf2c3f35,0xbedb3ef1bf043f0e,0xbe793e95beac3ec4,0xbd493dc9be163e48,0xbf7d3f7fbf803f80,0xbf713f75bf783f7b,0xbf5c3f62bf673f6d,0xbf3e3f46bf4e3f55,
0x3f6fbf673f5fbf55,0x3f7fbf7d3f7abf75,0x3f13bf043ee6bec4,0x3f4abf3e3f31bf22,0x3cc93d49bdfb3e48,0x3ea1be793e2fbdc9,0xbf093f18bf273f35,0xbe893eacbecf3ef1,
0x3eb8bedb3efcbf0e,0x3d97be163e60be95,0x3f51bf5c3f65bf6d,0x3f1dbf2c3f39bf46,0x3f80bf803f7ebf7b,0x3f73bf783f7cbf7f,0x3f58bf4e3f42bf35,0x3f77bf713f6abf62,
0x3f75bf7b3f7fbf80,0x3f46bf553f62bf6d,0x3ef1bf0e3f22bf35,0x3dc9be483e95bec4,0xbe953e48bdc90000,0xbf223f0ebef13ec4,0xbf623f55bf463f35,0xbf7f3f7bbf753f6d,
0xbe953e48bdc98000,0xbf223f0ebef13ec4,0xbf623f55bf463f35,0xbf7f3f7bbf753f6d,0xbf753f7bbf7f3f80,0xbf463f55bf623f6d,0xbef13f0ebf223f35,0xbdc93e48be953ec4,
0xbf583f67bf733f7b,0xbefc3f18bf313f46,0xbf6a3f5cbf4a3f35,0xbf7f3f80bf7c3f75,0x3f51bf3e3f27bf0e,0x3f7ebf783f6fbf62,0xbcc93e16be893ec4,0x3ee6beac3e60bdc9,
0x3f09bedb3ea1be48,0x3f5fbf4e3f39bf22,0xbecf3f04bf1d3f35,0x3d973d49be2f3e95,0x3f13bf2c3f42bf55,0x3dfbbe793eb8bef1,0x3f80bf7d3f77bf6d,0x3f65bf713f7abf7f,
0x3eacbef13f18bf35,0xbe793dc93d49be48,0xbf3e3f22bf043ec4,0xbf7d3f75bf673f55,0x3edbbe953e160000,0x3f5cbf463f2cbf0e,0x3f80bf7f3f78bf6d,0x3f4ebf623f71bf7b,
0xbf713f62bf4e3f35,0xbf783f7fbf803f7b,0xbf2c3f46bf5c3f6d,0xbe163e95bedb3f0e,0x3f67bf753f7dbf80,0x3f04bf223f3ebf55,0xbd49bdc93e79bec4,0xbf183ef1beac3e48,
0x3f27bf043eb8be48,0x3f7cbf713f5fbf46,0xbf1d3f3ebf583f6d,0x3cc93e16bea13ef1,0xbf653f4ebf313f0e,0xbf7a3f80bf7e3f75,0x3e89bedb3f13bf35,0xbecf3e79bd97bdc9,
0x3f42bf5c3f6fbf7b,0x3e2fbeac3efcbf22,0x3f4abf2c3f09bec4,0x3f80bf7d3f73bf62,0xbee63f18bf393f55,0x3e60bd49bdfb3e95,0xbf773f67bf513f35,0xbf6a3f78bf7f3f7f,
0xbf553f6dbf7b3f80,0xbe483ec4bf0e3f35,0x3f0ebec43e480000,0x3f7bbf6d3f55bf35,0x3f55bf6d3f7bbf80,0x3e48bec43f0ebf35,0xbf0e3ec4be480000,0xbf7b3f6dbf553f35,
0x3f0ebec43e488000,0x3f7bbf6d3f55bf35,0x3f55bf6d3f7bbf80,0x3e48bec43f0ebf35,0xbf0e3ec4be488000,0xbf7b3f6dbf553f35,0xbf553f6dbf7b3f80,0xbe483ec4bf0e3f35,
0xbd97be163eb8bf0e,0xbf513f2cbefc3e95,0x3f7ebf713f58bf35,0x3f39bf5c3f73bf7f,0x3ee6be793cc93e48,0x3f7abf673f4abf22,0xbf773f80bf7c3f6d,0xbecf3f18bf423f62,
0xbf7f3f7dbf6f3f55,0xbf133f3ebf5f3f75,0x3dfbbeac3f09bf35,0xbf313f04bea13dc9,0x3f65bf783f80bf7b,0x3e60bedb3f1dbf46,0x3e89bd49be2f3ec4,0x3f6abf4e3f27bef1,
0x3f80bf753f5cbf35,0x3f18bf463f67bf7b,0xbeac3dc93e16bec4,0xbf783f62bf3e3f0e,0xbf2c3ef1be790000,0xbf7d3f7fbf713f55,0xbedb3f22bf4e3f6d,0x3f04be953d493e48,
0x3d49be953f04bf35,0xbf4e3f22bedb3e48,0xbf713f7fbf7d3f6d,0xbe793ef1bf2c3f55,0xbf3e3f62bf783f80,0x3e163dc9beac3f0e,0x3f67bf463f18bec4,0x3f5cbf753f80bf7b,
0x3e603d49bea13f0e,0x3f77bf5c3f31bef1,0xbf6f3f4ebf1d3ec4,0xbf423f67bf7c3f7f,0x3f51bf713f7fbf7b,0xbdfbbe163ecfbf22,0x3cc93e79befc3f35,0x3f65bf3e3f09be95,
0x3f7abf803f73bf55,0x3e89bf043f39bf62,0xbeb83f18bf4a3f6d,0x3f27bedb3e2f3dc9,0xbf133eacbd97be48,0xbf7e3f7dbf6a3f46,0x3f80bf783f5fbf35,0x3ee6bf2c3f58bf75,
0x3f22bf553f75bf80,0xbef13e483dc9bec4,0xbf7f3f7bbf623f35,0xbe953f0ebf463f6d,0x3f46bf0e3e950000,0x3f62bf7b3f7fbf6d,0xbdc9be483ef1bf35,0xbf753f55bf223ec4,
0xbf463f0ebe958000,0xbf623f7bbf7f3f6d,0x3dc93e48bef13f35,0x3f75bf553f22bec4,0x3f22bf553f75bf80,0xbef13e483dc9bec4,0xbf7f3f7bbf623f35,0xbe953f0ebf463f6d,
0x3f6abf3e3efcbe48,0x3f27bf5c3f7abf7f,0xbf7c3f7dbf653f35,0xbdfb3edbbf313f62,0xbcc93eacbf1d3f55,0x3f73bf4e3f13be95,0xbf093e793d97bec4,0xbf773f80bf6f3f46,
0x3ecfbf2c3f5fbf7b,0xbf423f04be60bdc9,0x3e2f3e16bee63f35,0x3f7ebf673f39bef1,0x3f80bf713f4abf0e,0x3ea1bf183f51bf75,0xbf583f78bf7f3f6d,0x3e893d49beb83f22,
0x3e793dc9bedb3f35,0x3f80bf753f4ebf0e,0x3e16bef13f3ebf6d,0xbf713f46bf043e48,0x3f5cbf223eac0000,0x3f2cbf623f7dbf7b,0xbf183e953d49bec4,0xbf673f7fbf783f55,
0x3f78bf7f3f67bf35,0xbd49be953f18bf55,0xbf7d3f62bf2c3ec4,0xbeac3f22bf5c3f7b,0x3f04bf463f71bf80,0xbf3e3ef1be16be48,0xbf4e3f75bf803f6d,0x3edbbdc9be793f0e,
0xbe893f18bf583f7b,0x3f6fbf3e3ee6bdc9,0x3d97bedb3f39bf6d,0xbf7c3f5cbf1d3e95,0x3dfb3e79bf133f55,0x3f80bf713f42bef1,0xbea1bd493ecfbf35,0xbf7a3f7dbf5f3f22,
0x3f77bf4e3f09be48,0x3eb8bf2c3f65bf7f,0xbf7f3f67bf313ec4,0xbe2f3f04bf4a3f75,0x3f7ebf783f51bf0e,0xbcc9beac3f27bf62,0xbf733f80bf6a3f35,0x3e603e16befc3f46,
0xbec43f35bf6d3f80,0x3f6dbf353ec40000,0x3ec4bf353f6dbf80,0xbf6d3f35bec40000,0xbec43f35bf6d3f80,0x3f6dbf353ec40000,0x3ec4bf353f6dbf80,0xbf6d3f35bec40000,
0x3f6dbf353ec48000,0x3ec4bf353f6dbf80,0xbf6d3f35bec48000,0xbec43f35bf6d3f80,0x3f6dbf353ec48000,0x3ec4bf353f6dbf80,0xbf6d3f35bec48000,0xbec43f35bf6d3f80,
0xbf4a3f78bf7c3f55,0x3f31beacbd973ef1,0x3f65bf803f6fbf35,0xbf093e163e89bf22,0xbefc3f4ebf7a3f7b,0x3f6abf2c3ea13dc9,0x3f27bf673f80bf6d,0xbf513f04bdfbbe95,
0x3f1dbe79be2f3f0e,0x3f39bf713f7fbf62,0xbee63d493eb8bf35,0xbf583f7dbf773f46,0x3f5fbf183e603e48,0x3ecfbf3e3f73bf7f,0xbf423edbbcc9bec4,0xbf133f5cbf7e3f75,
0xbf5c3f7fbf713f35,0x3f2cbe95be163f0e,0x3f18bf623f80bf6d,0xbf673f22be79be48,0xbf783f46bedb0000,0xbd493ef1bf4e3f7b,0x3f7dbf753f3ebec4,0xbeacbdc93f04bf55,
0x3f04bdc9beac3f35,0x3f3ebf753f7dbf55,0xbf4e3ef1bd49bec4,0xbedb3f46bf783f7b,0xbe793f22bf673f80,0x3f80bf623f18be48,0xbe16be953f2cbf6d,0xbf713f7fbf5c3f0e,
0xbf313f71bf7e3f55,0x3f65bf183e2f3e95,0x3f7abf783f42bec4,0xbefc3d493ecfbf46,0xbf6f3f2cbe89be48,0xbd973f04bf583f7f,0x3f13be16bea13f35,0x3f1dbf673f80bf62,
0x3f39beacbdfb3f0e,0x3ee6bf4e3f7cbf75,0xbe60be793f27bf6d,0xbf5f3f80bf6a3f22,0xbeb83f3ebf773f7b,0x3f7fbf5c3f09bdc9,0x3f51bf7d3f73bf35,0xbf4a3edb3cc9bef1,
0x3dc9bf0e3f62bf80,0xbf753f7bbf463ec4,0x3f22be48be953f35,0x3ef1bf553f7fbf6d,0xbf7f3f55bef10000,0x3e953e48bf223f6d,0x3f46bf7b3f75bf35,0xbf623f0ebdc9bec4,
0xbf7f3f55bef18000,0x3e953e48bf223f6d,0x3f46bf7b3f75bf35,0xbf623f0ebdc9bec4,0xbdc93f0ebf623f80,0x3f75bf7b3f46bec4,0xbf223e483e95bf35,0xbef13f55bf7f3f6d,
0xbe2fbeac3f42bf7b,0xbf4a3f7dbf6f3f22,0xbf393f78bf773f35,0x3f73bf2c3e603e95,0xbf583f80bf653f0e,0x3f5fbf043cc93ef1,0x3f6abf183dfb3ec4,0xbd97bedb3f51bf7f,
0xbf7c3f71bf273e48,0x3f1dbe16beb83f46,0x3f31be79be893f35,0x3ea1bf3e3f7abf75,0x3f09bd49bee63f55,0x3efcbf5c3f80bf62,0x3ecfbf4e3f7ebf6d,0xbf7f3f67bf133dc9,
0xbf3e3e953e79bf35,0xbe163f22bf713f7b,0x3f67bf7f3f4ebec4,0xbf5c3ef13d49bf0e,0x3f80bf623f040000,0xbf183dc93edbbf55,0xbeac3f46bf7d3f6d,0x3f78bf753f2cbe48,
0xbf2c3f75bf783f35,0x3f7dbf463eac3e48,0xbedbbdc93f18bf6d,0xbf043f62bf803f55,0xbd49bef13f5cbf80,0xbf4e3f7fbf673f0e,0x3f71bf223e163ec4,0xbe79be953f3ebf7b,
0xbf733f78bf313e48,0x3f58bedbbdfb3f22,0x3efc3d49bf133f6d,0x3eb8bf4e3f7fbf62,0x3f42bf7d3f6abf0e,0xbf7c3f3ebe89be95,0xbf4a3eac3e60bf35,0x3cc93f04bf653f7f,
0x3ea13e79bf393f7b,0x3f09bf673f7ebf46,0x3f5fbf803f51bec4,0xbf6f3f18bd97bef1,0xbf273e163ecfbf55,0xbe2f3f2cbf773f75,0xbf1d3f71bf7a3f35,0x3f80bf5c3ee63dc9,
0x3e483ec4bf553f80,0x3f0ebf6d3f7bbf35,0xbf7b3f6dbf0e0000,0x3f55bec4be483f35,0xbe48bec43f55bf80,0xbf0e3f6dbf7b3f35,0x3f7bbf6d3f0e0000,0xbf553ec43e48bf35,
0x3f7bbf6d3f0e8000,0xbf553ec43e48bf35,0x3e483ec4bf553f80,0x3f0ebf6d3f7bbf35,0xbf7b3f6dbf0e8000,0x3f55bec4be483f35,0xbe48bec43f55bf80,0xbf0e3f6dbf7b3f35,
0x3f73bf183cc93f0e,0xbf09bd493f1dbf75,0x3efcbf673f7cbf35,0xbf6f3f78bf273dc9,0xbf7f3f5cbecfbe48,0x3f51beacbe893f46,0xbdfb3f2cbf7a3f6d,0x3f39bf7d3f65bef1,
0x3ea1bf4e3f80bf55,0xbf583f80bf4a3e95,0xbf5f3edb3e2fbf35,0x3eb83e79bf423f7f,0x3d973f04bf6a3f7b,0x3f13bf713f77bf22,0x3f7ebf3e3e603ec4,0xbf313e163ee6bf62,
0x3edbbf623f7dbf35,0xbf5c3f7fbf3e3e48,0x3f80bf463e793ec4,0xbf4e3e953eacbf55,0xbf713f75bf180000,0x3f78bf223d493f0e,0xbf2c3dc93f04bf6d,0x3e163ef1bf673f7b,
0xbf673ef13e16bf35,0x3f043dc9bf2c3f7b,0x3d49bf223f78bf6d,0xbf183f75bf713f0e,0x3eac3e95bf4e3f80,0x3e79bf463f80bf55,0xbf3e3f7fbf5c3ec4,0x3f7dbf623edb3e48,
0xbf7c3f2cbd97bf0e,0x3f4abe79becf3f62,0xbf313f7dbf5f3ec4,0x3f73bf713f093dc9,0x3e603edbbf653f7b,0x3e89bf4e3f80bf46,0x3f6fbf04bdfb3f35,0xbf273d493f13bf75,
0xbe2f3f3ebf7f3f55,0x3f1dbf783f6abef1,0x3f39be16befc3f6d,0xbea1beac3f58bf7f,0x3f7abf673ee63e48,0xbf773f183cc9bf22,0x3eb8bf5c3f7ebf35,0xbf423f80bf513e95,
0xbef1be483f46bf80,0x3dc93f0ebf753f6d,0x3e95bf553f7fbf35,0xbf223f7bbf623ec4,0x3f62bf7b3f220000,0xbf7f3f55be95bec4,0x3f75bf0ebdc93f35,0xbf463e483ef1bf6d,
0xbf623f7bbf228000,0x3f7fbf553e953ec4,0xbf753f0e3dc9bf35,0x3f46be48bef13f6d,0xbef1be483f46bf80,0x3dc93f0ebf753f6d,0x3e95bf553f7fbf35,0xbf223f7bbf623ec4,
0xbf393f80bf4a3e48,0x3f65bf783f133dc9,0xbe603f4ebf7f3f35,0x3efcbf713f6fbef1,0xbf6a3edb3e89bf55,0x3f42be16bf093f75,0xbf7c3f5cbea1bec4,0x3f7ebf2c3cc93f22,
0x3f31bd49bf1d3f7b,0xbee6be793f51bf7f,0x3f7abf18bd973f35,0xbf5f3eac3eb8bf62,0xbecf3f67bf773f0e,0x3f27bf7d3f58be95,0x3e2f3f04bf733f6d,0x3dfbbf3e3f80bf46,
0x3f7dbf22bd493f35,0xbf713ef13e79bf55,0x3f5cbe95bedb3f6d,0xbf3e3dc93f18bf7b,0x3f4ebf7f3f2c0000,0xbf673f75bf04be48,0x3f78bf623eac3ec4,0xbf803f46be16bf0e,
0x3e16bf463f80bf35,0xbeac3f62bf783f0e,0x3f04bf753f67bec4,0xbf2c3f7fbf4e3e48,0xbf18bdc93f3ebf80,0x3edb3e95bf5c3f7b,0xbe79bef13f71bf6d,0x3d493f22bf7d3f55,
0xbf4a3e163f13bf7b,0x3f39bd49bf273f7f,0xbf653eac3ecfbf6d,0x3f58be79befc3f75,0xbf773f043e60bf55,0x3f6fbedbbea13f62,0xbf7f3f2c3cc9bf35,0x3f7cbf18bdfb3f46,
0xbf1d3f7dbf513e48,0x3f31bf803f42bdc9,0xbee63f71bf6a3ec4,0x3f09bf783f5fbe95,0xbe893f5cbf7a3f0e,0x3eb8bf673f73bef1,0xbd973f3ebf803f35,0x3e2fbf4e3f7ebf22,
0x3f350000bf353f80,0xbf3500003f35bf80,0x3f350000bf353f80,0xbf3500003f35bf80,0x3f350000bf353f80,0xbf3500003f35bf80,0x3f350000bf353f80,0xbf3500003f35bf80,
0xbf353f80bf358000,0x3f35bf803f358000,0xbf353f80bf358000,0x3f35bf803f358000,0xbf353f80bf358000,0x3f35bf803f358000,0xbf353f80bf358000,0x3f35bf803f358000,
0xbf773e793f7abe48,0xbf6f3eac3f73be95,0xbf7f3d493f800000,0xbf7c3e163f7ebdc9,0xbf4a3f183f51bf0e,0xbf393f2c3f42bf22,0xbf653edb3f6abec4,0xbf583f043f5fbef1,
0x3e893f78be60bf7b,0x3eb83f71bea1bf75,0x3d973f80bcc9bf80,0x3e2f3f7dbdfbbf7f,0x3f1d3f4ebf13bf55,0x3f313f3ebf27bf46,0x3ee63f67becfbf6d,0x3f093f5cbefcbf62,
0x3f4e3f22bf3ebf35,0x3f673ef1bf5cbf0e,0x3f783e95bf71bec4,0x3f803dc9bf7dbe48,0x3e163f7fbd49bf80,0x3eac3f75be79bf7b,0x3f043f62bedbbf6d,0x3f2c3f46bf18bf55,
0x3f18bf46bf2c3f35,0x3edbbf62bf043f55,0x3e79bf75beac3f6d,0x3d49bf7fbe163f7b,0x3f7dbdc9bf808000,0x3f71be95bf783e48,0x3f5cbef1bf673ec4,0x3f3ebf22bf4e3f0e,
0xbecfbf713e893f7b,0xbf27bf4e3f093f62,0x3e2fbf78bea13f6d,0xbdfbbf80bcc93f7f,0x3f31bf2cbf4a3f0e,0x3ee6bf5cbf133f46,0x3f7abe16bf7f0000,0x3f5fbedbbf6f3e95,
0xbf6a3eac3f77be48,0xbf423f183f58bef1,0xbf7cbe793f733ec4,0xbf7e3d493f803dc9,0xbf39bf3e3f1d3f55,0xbf65bf043f513f22,0xbe60bf7d3d973f80,0xbefcbf673eb83f75,
0xbe95bf7b3dc93f80,0xbf22bf553ef13f6d,0xbf62bf0e3f463f35,0xbf7fbe483f753ec4,0xbf753e483f7f0000,0xbf463f0e3f62bec4,0xbef13f553f22bf35,0xbdc93f7b3e95bf6d,
0xbf753e483f7f8000,0xbf463f0e3f62bec4,0xbef13f553f22bf35,0xbdc93f7b3e95bf6d,0x3e953f7bbdc9bf80,0x3f223f55bef1bf6d,0x3f623f0ebf46bf35,0x3f7f3e48bf75bec4,
0xbe603f713ee6bf55,0x3e893f7dbcc9bf7f,0xbf6f3e793f7e0000,0xbf273f2c3f51bef1,0x3f7cbd49bf7fbe48,0x3f4abf04bf6a3e95,0x3f313f4ebefcbf6d,0x3f733edbbf58bf22,
0x3f7a3eacbf65bf0e,0x3f77be16bf80bdc9,0x3eb83f78bdfbbf80,0x3f423f3ebf13bf62,0xbe2fbf80bd973f7b,0xbf1dbf5c3ecf3f75,0x3f39bf18bf5f3ec4,0x3ea1bf67bf093f46,
0x3eacbf62bf183f35,0xbe79bf7fbd493f7b,0xbf3ebf463f043f6d,0xbf7dbe953f673f0e,0x3edb3f75be16bf80,0x3f5c3f22bf2cbf55,0x3f803dc9bf78bec4,0x3f4ebef1bf713e48,
0xbf71bef13f4e3f35,0xbf783dc93f803e48,0xbf2c3f223f5cbec4,0xbe163f753edbbf55,0x3f67be95bf7d8000,0x3f04bf46bf3e3f0e,0xbd49bf7fbe793f6d,0xbf18bf623eac3f7b,
0xbd973f783ecfbf55,0x3f133f67be89bf7f,0xbf7ebd493f7a3ec4,0xbf313f183f65be95,0xbea1bf7dbcc93f7b,0xbf58bf2c3f1d3f62,0x3f5fbeacbf7c0000,0x3eb8bf5cbf273f22,
0x3f7f3e79bf6abf0e,0x3f51bedbbf773dc9,0x3dfb3f803e60bf6d,0x3f393f4ebee6bf75,0xbf733e163f803e48,0xbf093f3e3f4abef1,0xbefcbf713e2f3f80,0xbf6fbf043f423f46,
0xbf0ebf6d3e483f80,0xbf7bbec43f553f35,0xbf553ec43f7b0000,0xbe483f6d3f0ebf35,0x3f0e3f6dbe48bf80,0x3f7b3ec4bf55bf35,0x3f55bec4bf7b0000,0x3e48bf6dbf0e3f35,
0xbf553ec43f7b8000,0xbe483f6d3f0ebf35,0x3f0e3f6dbe48bf80,0x3f7b3ec4bf55bf35,0x3f55bec4bf7b8000,0x3e48bf6dbf0e3f35,0xbf0ebf6d3e483f80,0xbf7bbec43f553f35,
0x3f423f4ebecfbf7b,0x3f7c3d49bf77bef1,0xbf4a3edb3f7a0000,0xbcc93f783ee6bf46,0xbf73bf043f393f55,0xbf583eac3f7e3dc9,0x3efcbf3ebf513ec4,0xbeb8bf7dbd973f75,
0x3f27bf18bf6a3e48,0xbe2fbf80be893f62,0x3f1d3f67be60bf80,0x3f803e79bf65bf22,0xbea13f5c3f31bf0e,0x3f093f71bdfbbf7f,0xbf5fbf2c3f133f6d,0xbf6f3e163f7f3e95,
0xbf80be953f5c3f35,0xbf183f223f67be48,0x3eac3f7f3e16bf6d,0x3f783ef1bf3ebf55,0x3f2c3f62be79bf80,0x3f7d3dc9bf71bf0e,0x3edbbf46bf4e3ec4,0xbf04bf753d493f7b,
0xbd493f753f04bf35,0x3f4e3f46bedbbf7b,0x3f71bdc9bf7dbec4,0x3e79bf62bf2c3f0e,0x3f3ebef1bf788000,0xbe16bf7fbeac3f55,0xbf67bf223f183f6d,0xbf5c3e953f803e48,
0x3f09bf2cbf653e48,0xbefcbf78bcc93f75,0x3ecf3f7d3dfbbf6d,0x3f7f3eacbf51bf46,0xbf7cbedb3f423f55,0xbf1d3f183f6fbdc9,0x3f31bf04bf770000,0xbea1bf80be603f62,
0xbf58bf3e3ee63f7b,0xbf5f3e793f803e95,0x3f6abe16bf7ebec4,0x3d97bf71bf133f22,0xbe2f3f673f27bf0e,0x3f4a3f4ebeb8bf7f,0xbf39bf5c3e893f80,0xbf733d493f7a3ef1,
0xbf46bf553e953f80,0xbf623e483f7f3ec4,0x3dc93f7b3ef1bf35,0x3f753f0ebf22bf6d,0x3f22bf0ebf750000,0xbef1bf7bbdc93f6d,0xbf7fbe483f623f35,0xbe953f553f46bec4,
0xbf223f0e3f758000,0x3ef13f7b3dc9bf6d,0x3f7f3e48bf62bf35,0x3e95bf55bf463ec4,0xbf46bf553e953f80,0xbf623e483f7f3ec4,0x3dc93f7b3ef1bf35,0x3f753f0ebf22bf6d,
0x3f6fbd49bf77bf0e,0xbd97bf78bf093f22,0xbf133f183f730000,0x3f1d3f71bcc9bf75,0x3f313f67bdfbbf7b,0x3f65be16bf7cbef1,0xbf7abf043f273f6d,0xbefc3f2c3f6abdc9,
0xbeb8bf80be893f55,0xbf7fbe793f583f46,0x3f513f4ebea1bf80,0x3f4abeacbf80be95,0x3f39bedbbf7ebe48,0xbee6bf7dbe2f3f62,0xbe603f5c3f42bec4,0x3f5f3f3ebecfbf7f,
0x3e793f7f3edbbf35,0x3f803e95bf4ebf55,0x3e16bf62bf3e3ec4,0xbf71bf223f043f7b,0x3f5c3f46beacbf80,0x3f2cbef1bf7dbe48,0xbf18bf75bd493f6d,0xbf673dc93f783f0e,
0x3f783dc9bf67bf35,0xbd49bf75bf183f0e,0xbf7dbef13f2c3f6d,0xbeac3f463f5cbe48,0x3f04bf22bf718000,0xbf3ebf623e163f7b,0xbf4e3e953f803ec4,0x3edb3f7f3e79bf55,
0xbf5f3e163f7a3f0e,0x3ecf3f803ea1bf46,0x3f42beacbf80bec4,0xbf13bf78bdfb3f62,0xbf1d3f043f7c3e48,0x3f393f67bd97bf75,0x3ee6bf2cbf6f0000,0xbf58bf4e3e893f7f,
0x3efc3f7d3e60bf55,0x3f6abd49bf73bf22,0xbf27bf71bcc93f6d,0xbf513e793f7e3ef1,0x3f4a3f5cbe2fbf7b,0x3f31bedbbf7fbe95,0xbf65bf3e3eb83f80,0xbf093f183f773dc9,
0xbf6dbf353ec43f80,0xbec43f353f6d0000,0x3f6d3f35bec4bf80,0x3ec4bf35bf6d0000,0xbf6dbf353ec43f80,0xbec43f353f6d0000,0x3f6d3f35bec4bf80,0x3ec4bf35bf6d0000,
0xbec43f353f6d8000,0x3f6d3f35bec4bf80,0x3ec4bf35bf6d8000,0xbf6dbf353ec43f80,0xbec43f353f6d8000,0x3f6d3f35bec4bf80,0x3ec4bf35bf6d8000,0xbf6dbf353ec43f80,
0x3dfbbf5cbf513e48,0xbf80bedb3f273f75,0xbea13f3e3f6a0000,0x3f7a3f18befcbf7f,0xbe89bf7dbf093f0e,0xbf6fbd493f653f46,0x3d973f713f31bec4,0x3f7c3e79bf4abf62,
0xbf7ebf043f133f7b,0xbcc93f673f42be95,0x3f733f2cbecfbf80,0x3e60bf4ebf5f3dc9,0xbf77be163f583f55,0x3eb83f803ee6bf22,0x3f7f3eacbf39bf6d,0xbe2fbf78bf1d3ef1,
0x3f5cbdc9bf71bf35,0xbf2cbf75be163f55,0xbf183ef13f803ec4,0x3f673f46be79bf7b,0x3f783f22bedbbf80,0x3d49bf62bf4e3e48,0xbf7dbe953f3e3f6d,0x3eac3f7f3f04bf0e,
0xbf04bf7fbeac3f35,0xbf3e3e953f7d3f0e,0x3f4e3f62bd49bf6d,0x3edbbf22bf78be48,0x3e79bf46bf678000,0xbf80bef13f183f7b,0x3e163f753f2cbec4,0x3f713dc9bf5cbf55,
0x3f803edbbf1dbf7b,0xbea1bf7dbf133ef1,0xbf58bf5c3d973f6d,0xbe893f3e3f6f3dc9,0x3ecf3f803efcbf0e,0x3f42be79bf7abf22,0x3e2fbf4ebf650000,0xbf7ebeac3f313f75,
0xbcc9bf67bf4a3e48,0xbf73be163f513f62,0xbf093f043f7f3ec4,0x3f773f2cbeb8bf7f,0x3f6a3d49bf5fbf55,0xbf27bf78be603f46,0xbf7cbf183ee63f80,0x3dfb3f713f39be95,
0xbf7fbf0e3ef13f80,0x3e953f7b3f22bec4,0x3f46be48bf75bf35,0xbf62bf553dc93f6d,0xbdc93f553f620000,0x3f753e48bf46bf6d,0xbf22bf7bbe953f35,0xbef13f0e3f7f3ec4,
0xbdc93f553f628000,0x3f753e48bf46bf6d,0xbf22bf7bbe953f35,0xbef13f0e3f7f3ec4,0x3f7f3f0ebef1bf80,0xbe95bf7bbf223ec4,0xbf463e483f753f35,0x3f623f55bdc9bf6d,
0xbf51bf67bd973f55,0xbdfb3f4e3f6a3dc9,0xbcc93f5c3f5f0000,0x3f653d49bf58bf62,0xbe603f3e3f733e48,0x3f773e79bf39bf75,0x3f6f3e16bf4abf6d,0xbf42bf71be2f3f46,
0xbf133edb3f7f3f0e,0x3f7e3f18becfbf7f,0x3f803f04befcbf80,0xbee6bf80bf093ef1,0x3f7a3f2cbea1bf7b,0xbe89bf78bf313e95,0xbeb8bf7dbf1d3ec4,0xbf273eac3f7c3f22,
0xbf3ebf75be793f35,0xbe163f463f713e48,0x3f673dc9bf4ebf6d,0xbf5cbf62bd493f55,0x3f803ef1bf04bf80,0xbf18bf7fbedb3f0e,0xbeac3f223f7d3ec4,0x3f783e95bf2cbf7b,
0xbf2c3e953f783f35,0x3f7d3f22beacbf7b,0xbedbbf7fbf183ec4,0xbf043ef13f803f0e,0xbd49bf62bf5c8000,0xbf4e3dc93f673f55,0x3f713f46be16bf6d,0xbe79bf75bf3e3e48,
0xbf65bf5cbcc93f55,0x3e603f713f4abdc9,0xbe893f2c3f7c3ec4,0x3f6a3e16bf42bf75,0x3f7f3f18beb8bf7b,0xbf13bf80befc3ef1,0xbdfbbf67bf580000,0xbf313e793f733f46,
0xbee63f043f803f0e,0x3f7a3eacbf1dbf7f,0x3f773f3ebe2fbf6d,0xbecfbf7dbf273e95,0x3d97bf4ebf6fbe48,0xbf513d493f5f3f62,0xbf7ebedb3f093f80,0x3f393f783ea1bf22,
0xbf7bbec43f0e3f80,0x3f553f6d3e48bf35,0xbe48bf6dbf550000,0xbf0e3ec43f7b3f35,0x3f7b3ec4bf0ebf80,0xbf55bf6dbe483f35,0x3e483f6d3f550000,0x3f0ebec4bf7bbf35,
0x3e483f6d3f558000,0x3f0ebec4bf7bbf35,0xbf7bbec43f0e3f80,0x3f553f6d3e48bf35,0xbe48bf6dbf558000,0xbf0e3ec43f7b3f35,0x3f7b3ec4bf0ebf80,0xbf55bf6dbe483f35,
0xbf65be163f393f7b,0x3f7a3f3ebdfbbf62,0x3e893f713f510000,0x3ecfbf04bf7fbf22,0x3f27be79bf6fbf55,0xbf7cbedb3efc3f7f,0xbf1dbf80bf093ec4,0xbcc93f4e3f733e95,
0x3ee63f7d3f31be48,0x3e60bf2cbf7ebef1,0x3f773eacbf13bf80,0xbf6abf5cbd973f46,0xbf42bf78beb83f0e,0x3e2f3f673f5f3dc9,0xbf4a3d493f583f6d,0x3f803f18bea1bf75,
0xbedb3ef13f7d3f35,0x3f5c3dc9bf3ebf7b,0xbf80bf223e793f6d,0x3f4e3f753eacbf0e,0x3f713e95bf18bf80,0xbf78bf463d493f55,0x3f2c3f7f3f04bec4,0xbe16bf62bf67be48,
0x3f673f623e16bf35,0xbf04bf7fbf2c3e48,0xbd493f463f783ec4,0x3f18be95bf71bf55,0xbeacbf75bf4e8000,0xbe793f223f803f0e,0x3f3ebdc9bf5cbf6d,0xbf7dbef13edb3f7b,
0x3f133f803f27be48,0xbdfbbf5cbf6fbe95,0x3f803f18be89bf6d,0xbf65bf67be603f22,0x3f09beacbf73bf55,0xbf5fbe163f313f7f,0xbecfbf78bf4a0000,0xbd973f3e3f7c3ef1,
0x3f513d49bf42bf7b,0xbf7ebf043eb83f75,0xbcc9bf4ebf77bec4,0xbee63edb3f7a3f46,0xbf58bf71bea13f0e,0x3efc3f7d3f39bdc9,0xbf6abe793f1d3f80,0x3f7f3f2cbe2fbf62,
0xbf62be483f223f80,0x3f7f3f0ebe95bf6d,0xbf75bf55bdc93f35,0x3f463f7b3ef1bec4,0xbef1bf7bbf460000,0x3dc93f553f753ec4,0x3e95bf0ebf7fbf35,0xbf223e483f623f6d,
0x3ef13f7b3f468000,0xbdc9bf55bf75bec4,0xbe953f0e3f7f3f35,0x3f22be48bf62bf6d,0xbf62be483f223f80,0x3f7f3f0ebe95bf6d,0xbf75bf55bdc93f35,0x3f463f7b3ef1bec4,
0xbcc93f3e3f7e3f0e,0x3ea1bf04bf7cbf46,0x3f093f7d3f420000,0xbe89bf67bf6abe95,0xbf6fbeac3efc3f7b,0x3f7f3f18be60bf62,0xbf133e793f653f6d,0x3f4a3d49bf39bf7f,
0x3f803f2cbdfbbf55,0xbf73bf5cbe2f3f22,0x3f583e16bf27bf80,0xbf77bedb3ecf3f75,0x3eb83f713f5f3e48,0xbd97bf4ebf7abef1,0x3f513f783ee6bec4,0xbf1dbf80bf313dc9,
0x3f7d3f463d49bf35,0xbf71bf62be793f0e,0x3f5c3f753edbbec4,0xbf3ebf7fbf183e48,0x3f4e3dc9bf2cbf80,0xbf67be953f043f7b,0x3f783ef1beacbf6d,0xbf80bf223e163f55,
0x3e16bf22bf80bf35,0xbeac3ef13f783f55,0x3f04be95bf67bf6d,0xbf2c3dc93f4e3f7b,0xbf18bf7fbf3e8000,0x3edb3f753f5c3e48,0xbe79bf62bf71bec4,0x3d493f463f7d3f0e,
0xbdfbbf4ebf7cbf0e,0x3cc93f3e3f7f3f22,0xbea1bf67bf6fbec4,0x3e603f5c3f773ef1,0xbefcbf78bf58be48,0x3ecf3f713f653e95,0xbf27bf80bf390000,0x3f133f7d3f4a3dc9,
0xbf7ebf183e2f3f55,0x3f803f2cbd97bf46,0xbf73bedb3eb83f6d,0x3f7a3f04be89bf62,0xbf5fbe793f093f7b,0x3f6a3eacbee6bf75,0xbf42bd493f313f80,0x3f513e16bf1dbf7f,
0x3f350000bf353f80,0xbf3500003f35bf80,0x3f350000bf353f80,0xbf3500003f35bf80,0x3f350000bf353f80,0xbf3500003f35bf80,0x3f350000bf353f80,0xbf3500003f35bf80,
0xbf353f80bf358000,0x3f35bf803f358000,0xbf353f80bf358000,0x3f35bf803f358000,0xbf353f80bf358000,0x3f35bf803f358000,0xbf353f80bf358000,0x3f35bf803f358000,
0xbefc3f5c3f09bf55,0xbecf3f673ee6bf62,0xbf273f3e3f31bf35,0xbf133f4e3f1dbf46,0xbdfb3f7d3e2fbf7b,0xbcc93f803d97bf7f,0xbea13f713eb8bf6d,0xbe603f783e89bf75,
0x3f5f3f04bf58bf0e,0x3f6a3edbbf65bef1,0x3f423f2cbf39bf35,0x3f513f18bf4abf22,0x3f7e3e16bf7cbe48,0x3f803d49bf7fbdc9,0x3f733eacbf6fbec4,0x3f7a3e79bf77be95,
0x3f18bf46bf2c3f35,0x3edbbf62bf043f55,0x3e79bf75beac3f6d,0x3d49bf7fbe163f7b,0x3f7dbdc9bf800000,0x3f71be95bf783e48,0x3f5cbef1bf673ec4,0x3f3ebf22bf4e3f0e,
0xbf4ebf223f3e3f35,0xbf67bef13f5c3f0e,0xbf78be953f713ec4,0xbf80bdc93f7d3e48,0xbe16bf7f3d493f80,0xbeacbf753e793f7b,0xbf04bf623edb3f6d,0xbf2cbf463f183f55,
0xbeb83f673efcbf55,0xbd973f7d3e60bf75,0xbf513f043f65bec4,0xbf1d3f3e3f39bf22,0xbf80bd493f7e3e48,0xbf733e793f7cbdc9,0xbf58bf183f423f35,0xbf77beac3f6a3ef1,
0x3f6f3edbbf5fbf0e,0x3f7f3e16bf7abe95,0x3f133f5cbee6bf6d,0x3f4a3f2cbf31bf46,0x3cc93f803dfbbf7b,0x3ea13f78be2fbf7f,0xbf093f4e3f27bf35,0xbe893f713ecfbf62,
0x3e953f7bbdc9bf80,0x3f223f55bef1bf6d,0x3f623f0ebf46bf35,0x3f7f3e48bf75bec4,0x3f75be48bf7f0000,0x3f46bf0ebf623ec4,0x3ef1bf55bf223f35,0x3dc9bf7bbe953f6d,
0x3f75be48bf7f8000,0x3f46bf0ebf623ec4,0x3ef1bf55bf223f35,0x3dc9bf7bbe953f6d,0xbe95bf7b3dc93f80,0xbf22bf553ef13f6d,0xbf62bf0e3f463f35,0xbf7fbe483f753ec4,
0xbf09bf673ea13f7b,0xbf5fbf183f393f46,0x3ecfbf5cbf1d3f35,0xbd97bf80be2f3f75,0xbf133f3e3f42bf0e,0xbdfb3f783eb8bf62,0xbf80be163f773ec4,0xbf653eac3f7abdc9,
0xbf583edb3f73be48,0xbefc3f4e3f31bf22,0xbf6abf043f4a3f35,0xbf7fbd493f7c3e95,0x3f513f2cbf27bf55,0x3f7e3e79bf6fbef1,0xbcc93f7d3e89bf6d,0x3ee63f71be60bf7f,
0x3f713ef1bf4ebf35,0x3f78bdc9bf80be48,0x3f2cbf22bf5c3ec4,0x3e16bf75bedb3f55,0xbf673e953f7d0000,0xbf043f463f3ebf0e,0x3d493f7f3e79bf6d,0x3f183f62beacbf7b,
0x3eacbf62bf183f35,0xbe79bf7fbd493f7b,0xbf3ebf463f043f6d,0xbf7dbe953f673f0e,0x3edb3f75be16bf80,0x3f5c3f22bf2cbf55,0x3f803dc9bf78bec4,0x3f4ebef1bf713e48,
0xbf423f043f6fbe48,0xbe2f3f713efcbf46,0xbf4abf3e3f093f6d,0xbf80be163f733ef1,0x3ee6bf4ebf393f0e,0xbe60bf80bdfb3f75,0x3f773edbbf51bf35,0x3f6abe79bf7fbdc9,
0x3f273f5cbeb8bf7b,0x3f7c3eacbf5fbf22,0xbf1d3f2c3f58bec4,0x3cc93f7d3ea1bf62,0xbf65bf183f313f55,0xbf7a3d493f7e3e95,0x3e89bf67bf133f35,0xbecfbf783d973f7f,
0xbf0ebf6d3e483f80,0xbf7bbec43f553f35,0xbf553ec43f7b0000,0xbe483f6d3f0ebf35,0x3f0e3f6dbe48bf80,0x3f7b3ec4bf55bf35,0x3f55bec4bf7b0000,0x3e48bf6dbf0e3f35,
0xbf553ec43f7b8000,0xbe483f6d3f0ebf35,0x3f0e3f6dbe48bf80,0x3f7b3ec4bf55bf35,0x3f55bec4bf7b8000,0x3e48bf6dbf0e3f35,0xbf0ebf6d3e483f80,0xbf7bbec43f553f35,
0x3f7f3e16bf6fbf0e,0x3f13bf2cbf5f3e95,0xbdfb3f713f09bf35,0x3f313f5cbea1bf7f,0xbf653e793f803e48,0xbe603f673f1dbf22,0xbe89bf80be2f3f6d,0xbf6abf183f273f62,
0xbd97bf7dbeb83f55,0xbf51bf3e3efc3f75,0x3f7e3eacbf58bf35,0x3f39bf04bf733dc9,0x3ee63f78bcc9bf7b,0x3f7a3edbbf4abf46,0xbf773d493f7c3ec4,0xbecf3f4e3f42bef1,
0xbd493f753f04bf35,0x3f4e3f46bedbbf7b,0x3f71bdc9bf7dbec4,0x3e79bf62bf2c3f0e,0x3f3ebef1bf780000,0xbe16bf7fbeac3f55,0xbf67bf223f183f6d,0xbf5c3e953f803e48,
0x3f803e95bf5cbf35,0x3f18bf22bf673e48,0xbeacbf7fbe163f6d,0xbf78bef13f3e3f55,0xbf2cbf623e793f80,0xbf7dbdc93f713f0e,0xbedb3f463f4ebec4,0x3f043f75bd49bf7b,
0xbf7abd493f733f0e,0xbe893f5c3f39bef1,0x3eb8bf4ebf4a3ec4,0xbf27bf673e2f3f7f,0x3f133f71bd97bf7b,0x3f7e3e16bf6abf22,0xbf80be793f5f3f35,0xbee63f3e3f58be95,
0x3e603f803ea1bf55,0x3f773f04bf31bf62,0xbf6fbf183f1d3f6d,0xbf423edb3f7c3dc9,0x3f51beacbf7fbe48,0xbdfbbf7dbecf3f46,0x3cc93f783efcbf35,0x3f653f2cbf09bf75,
0x3f463f55be95bf80,0x3f62be48bf7fbec4,0xbdc9bf7bbef13f35,0xbf75bf0e3f223f6d,0xbf223f0e3f750000,0x3ef13f7b3dc9bf6d,0x3f7f3e48bf62bf35,0x3e95bf55bf463ec4,
0x3f22bf0ebf758000,0xbef1bf7bbdc93f6d,0xbf7fbe483f623f35,0xbe953f553f46bec4,0x3f463f55be95bf80,0x3f62be48bf7fbec4,0xbdc9bf7bbef13f35,0xbf75bf0e3f223f6d,
0xbecf3f3e3f5fbe48,0x3f423f5cbe60bf7f,0xbe2fbf7dbee63f35,0xbf7ebedb3f393f62,0xbf80beac3f4a3f55,0xbea13f4e3f51be95,0x3f58be79bf7fbec4,0xbe89bf80beb83f46,
0x3f6a3f2cbefcbf7b,0x3f27bf04bf7abdc9,0xbf7cbe163f653f35,0xbdfb3f673f31bef1,0xbcc93f713f1dbf0e,0x3f733f18bf13bf75,0xbf09bf78bd973f6d,0xbf77bd493f6f3f22,
0xbf78bdc93f673f35,0x3d493f753f18bf0e,0x3f7d3ef1bf2cbf6d,0x3eacbf46bf5c3e48,0xbf043f223f710000,0x3f3e3f62be16bf7b,0x3f4ebe95bf80bec4,0xbedbbf7fbe793f55,
0x3e793f7f3edbbf35,0x3f803e95bf4ebf55,0x3e16bf62bf3e3ec4,0xbf71bf223f043f7b,0x3f5c3f46beacbf80,0x3f2cbef1bf7dbe48,0xbf18bf75bd493f6d,0xbf673dc93f783f0e,
0xbf77bf183f093f7b,0xbeb83f3e3f65bdc9,0x3f7f3edbbf31bf6d,0x3e2fbf5cbf4a3e95,0xbf7ebe793f513f55,0x3cc93f713f27bef1,0x3f733d49bf6abf35,0xbe60bf7dbefc3f22,
0xbe893f4e3f58be48,0x3f6f3f2cbee6bf7f,0x3d97bf67bf393ec4,0xbf7cbf043f1d3f75,0x3dfb3f783f13bf0e,0x3f803eacbf42bf62,0xbea1bf80becf3f35,0xbf7abe163f5f3f46,
0xbf6dbf353ec43f80,0xbec43f353f6d0000,0x3f6d3f35bec4bf80,0x3ec4bf35bf6d0000,0xbf6dbf353ec43f80,0xbec43f353f6d0000,0x3f6d3f35bec4bf80,0x3ec4bf35bf6d0000,
0xbec43f353f6d8000,0x3f6d3f35bec4bf80,0x3ec4bf35bf6d8000,0xbf6dbf353ec43f80,0xbec43f353f6d8000,0x3f6d3f35bec4bf80,0x3ec4bf35bf6d8000,0xbf6dbf353ec43f80,
0xbf1dbf78be2f3f55,0xbf393eac3f7f3ef1,0x3ee63f803eb8bf35,0x3f58be16bf77bf22,0xbf5fbf4e3e603f7b,0xbecf3f2c3f733dc9,0x3f423f67bcc9bf6d,0x3f13bf04bf7ebe95,
0xbf4a3e793f7c3f0e,0x3f313f713d97bf62,0x3f65bd49bf6fbf35,0xbf09bf7dbe893f46,0xbefc3f183f7a3e48,0x3f6a3f3ebea1bf7f,0x3f27bedbbf80bec4,0xbf51bf5c3dfb3f75,
0xbf04bf7fbeac3f35,0xbf3e3e953f7d3f0e,0x3f4e3f62bd49bf6d,0x3edbbf22bf78be48,0x3e79bf46bf670000,0xbf80bef13f183f7b,0x3e163f753f2cbec4,0x3f713dc9bf5cbf55,
0xbf5c3dc93f713f35,0x3f2c3f753e16bf55,0x3f18bef1bf80bec4,0xbf67bf463e793f7b,0xbf78bf223edb3f80,0xbd493f623f4ebe48,0x3f7d3e95bf3ebf6d,0xbeacbf7fbf043f0e,
0xbf39bf71bdfb3f55,0xbee63f183f7c3e95,0x3e603f783f27bec4,0x3f5fbd49bf6abf46,0x3eb8bf2cbf77be48,0xbf7fbf043f093f7f,0xbf513e163f733f35,0x3f4a3f673cc9bf62,
0xbf313eac3f7e3f0e,0x3f653f4ebe2fbf75,0x3f7a3e79bf42bf6d,0xbefcbf80becf3f22,0xbf6fbf3e3e893f7b,0xbd973f5c3f58bdc9,0x3f133f7d3ea1bf35,0x3f1dbedbbf80bef1,
0x3f7f3f0ebef1bf80,0xbe95bf7bbf223ec4,0xbf463e483f753f35,0x3f623f55bdc9bf6d,0x3dc9bf55bf620000,0xbf75be483f463f6d,0x3f223f7b3e95bf35,0x3ef1bf0ebf7fbec4,
0x3dc9bf55bf628000,0xbf75be483f463f6d,0x3f223f7b3e95bf35,0x3ef1bf0ebf7fbec4,0xbf7fbf0e3ef13f80,0x3e953f7b3f22bec4,0x3f46be48bf75bf35,0xbf62bf553dc93f6d,
0x3f7c3eacbf27bf7b,0xbf1dbf7dbeb83f22,0xbf31bf78be893f35,0xbea13f2c3f7a3e95,0xbf09bf80bee63f0e,0xbefc3f043f803ef1,0xbecf3f183f7e3ec4,0x3f7f3edbbf13bf7f,
0xbe2fbf71bf423e48,0xbf4a3e163f6f3f46,0xbf393e793f773f35,0x3f733f3ebe60bf75,0xbf583d493f653f55,0x3f5f3f5cbcc9bf62,0x3f6a3f4ebdfbbf6d,0xbd97bf67bf513dc9,
0x3f2cbe95bf78bf35,0xbf7dbf223eac3f7b,0x3edb3f7f3f18bec4,0x3f04bef1bf80bf0e,0x3d493f623f5c0000,0x3f4ebdc9bf67bf55,0xbf71bf463e163f6d,0x3e793f753f3ebe48,
0xbf3ebf75be793f35,0xbe163f463f713e48,0x3f673dc9bf4ebf6d,0xbf5cbf62bd493f55,0x3f803ef1bf04bf80,0xbf18bf7fbedb3f0e,0xbeac3f223f7d3ec4,0x3f783e95bf2cbf7b,
0xbea1bf78bf393e48,0xbf093edb3f7e3f22,0xbf5fbd493f513f6d,0x3f6f3f4ebd97bf62,0x3f273f7d3ecfbf0e,0x3e2fbf3ebf77be95,0x3f1dbeacbf7abf35,0xbf80bf043ee63f7f,
0xbf73be793f313f7b,0x3f583f673dfbbf46,0x3efc3f803f13bec4,0x3eb8bf18bf7fbef1,0x3f42be16bf6abf55,0xbf7cbf2c3e893f75,0xbf4abf71be603f35,0x3cc93f5c3f653dc9,
0xbf7bbec43f0e3f80,0x3f553f6d3e48bf35,0xbe48bf6dbf550000,0xbf0e3ec43f7b3f35,0x3f7b3ec4bf0ebf80,0xbf55bf6dbe483f35,0x3e483f6d3f550000,0x3f0ebec4bf7bbf35,
0x3e483f6d3f558000,0x3f0ebec4bf7bbf35,0xbf7bbec43f0e3f80,0x3f553f6d3e48bf35,0xbe48bf6dbf558000,0xbf0e3ec43f7b3f35,0x3f7b3ec4bf0ebf80,0xbf55bf6dbe483f35,
0xbea13f183f803f0e,0x3f583d49bf4abf75,0x3f5f3f673e2fbf35,0xbeb8bf78bf423dc9,0xbd97bf5cbf6abe48,0xbf133eac3f773f46,0xbf7ebf2c3e603f6d,0x3f313f7d3ee6bef1,
0x3f733f4ebcc9bf55,0xbf09bf80bf1d3e95,0x3efcbedbbf7cbf35,0xbf6fbe793f273f7f,0xbf7fbf043ecf3f7b,0x3f513f713e89bf22,0xbdfb3f3e3f7a3ec4,0x3f39be16bf65bf62,
0x3f673f623e16bf35,0xbf04bf7fbf2c3e48,0xbd493f463f783ec4,0x3f18be95bf71bf55,0xbeacbf75bf4e0000,0xbe793f223f803f0e,0x3f3ebdc9bf5cbf6d,0xbf7dbef13edb3f7b,
0x3edbbef1bf7dbf35,0xbf5cbdc93f3e3f7b,0x3f803f22be79bf6d,0xbf4ebf75beac3f0e,0xbf71be953f183f80,0x3f783f46bd49bf55,0xbf2cbf7fbf043ec4,0x3e163f623f673e48,
0x3e2fbf2cbf7fbf0e,0xbf1d3e793f6a3f62,0xbf39bf7dbefc3ec4,0x3ea13f713f583dc9,0xbf7abedb3ee63f7b,0x3f773f4e3cc9bf46,0xbeb83f043f7e3f35,0x3f42bd49bf51bf75,
0xbf7cbf3e3d973f55,0x3f4a3f783ecfbef1,0xbf313e163f5f3f6d,0x3f733eacbf09bf7f,0x3e603f673f653e48,0x3e89bf18bf80bf22,0x3f6f3f5c3dfbbf35,0xbf27bf80bf133e95,
0x3f623e48bf22bf80,0xbf7fbf0e3e953f6d,0x3f753f553dc9bf35,0xbf46bf7bbef13ec4,0x3ef13f7b3f460000,0xbdc9bf55bf75bec4,0xbe953f0e3f7f3f35,0x3f22be48bf62bf6d,
0xbef1bf7bbf468000,0x3dc93f553f753ec4,0x3e95bf0ebf7fbf35,0xbf223e483f623f6d,0x3f623e48bf22bf80,0xbf7fbf0e3e953f6d,0x3f753f553dc9bf35,0xbf46bf7bbef13ec4,
0xbf31bf80bf1d3e48,0x3ee63f783f513dc9,0xbf7abf4ebd973f35,0x3f5f3f713eb8bef1,0x3ecfbedbbf77bf55,0xbf273e163f583f75,0xbe2fbf5cbf73bec4,0xbdfb3f2c3f803f22,
0xbf393d493f4a3f7b,0x3f653e79bf13bf7f,0xbe603f183f7f3f35,0x3efcbeacbf6fbf62,0xbf6abf67be893f0e,0x3f423f7d3f09be95,0xbf7cbf043ea13f6d,0x3f7e3f3ebcc9bf46,
0xbe163f223f803f35,0x3eacbef1bf78bf55,0xbf043e953f673f6d,0x3f2cbdc9bf4ebf7b,0x3f183f7f3f3e0000,0xbedbbf75bf5cbe48,0x3e793f623f713ec4,0xbd49bf46bf7dbf0e,
0x3f7d3f463d49bf35,0xbf71bf62be793f0e,0x3f5c3f753edbbec4,0xbf3ebf7fbf183e48,0x3f4e3dc9bf2cbf80,0xbf67be953f043f7b,0x3f783ef1beacbf6d,0xbf80bf223e163f55,
0x3f1dbe16bf51bf7b,0xbf313d493f423f7f,0x3ee6beacbf6abf6d,0xbf093e793f5f3f75,0x3e89bf04bf7abf55,0xbeb83edb3f733f62,0x3d97bf2cbf80bf35,0xbe2f3f183f7e3f46,
0xbf4abf7dbf133e48,0x3f393f803f27bdc9,0xbf65bf71becf3ec4,0x3f583f783efcbe95,0xbf77bf5cbe603f0e,0x3f6f3f673ea1bef1,0xbf7fbf3ebcc93f35,0x3f7c3f4e3dfbbf22,
0x3f003f003f003f00,0x3f003f003f003f00,0x3f003f003f003f00,0x3f003f003f003f00,0x3f003f003f003f00,0x3f003f003f003f00,0x3f003f003f003f00,0x3f003f003f003f00,
0xbf003f00bf003f00,0xbf003f00bf003f00,0xbf003f00bf003f00,0xbf003f00bf003f00,0xbf003f00bf003f00,0xbf003f00bf003f00,0xbf003f00bf003f00,0xbf003f00bf003f00,
0xbf77bf78bf7abf7b,0xbf6fbf71bf73bf75,0xbf7fbf80bf80bf80,0xbf7cbf7dbf7ebf7f,0xbf4abf4ebf51bf55,0xbf39bf3ebf42bf46,0xbf65bf67bf6abf6d,0xbf58bf5cbf5fbf62,
0x3e893e793e603e48,0x3eb83eac3ea13e95,0x3d973d493cc98000,0x3e2f3e163dfb3dc9,0x3f1d3f183f133f0e,0x3f313f2c3f273f22,0x3ee63edb3ecf3ec4,0x3f093f043efc3ef1,
0x3f183f223f2c3f35,0x3edb3ef13f043f0e,0x3e793e953eac3ec4,0x3d493dc93e163e48,0x3f7d3f7f3f803f80,0x3f713f753f783f7b,0x3f5c3f623f673f6d,0x3f3e3f463f4e3f55,
0xbf4ebf46bf3ebf35,0xbf67bf62bf5cbf55,0xbf78bf75bf71bf6d,0xbf80bf7fbf7dbf7b,0xbe16bdc9bd498000,0xbeacbe95be79be48,0xbf04bef1bedbbec4,0xbf2cbf22bf18bf0e,
0x3ecf3eac3e893e48,0x3f273f183f093ef1,0xbe2fbe79bea1bec4,0x3dfb3d49bcc9bdc9,0xbf31bf3ebf4abf55,0xbee6bf04bf13bf22,0xbf7abf7dbf7fbf80,0xbf5fbf67bf6fbf75,
0x3f6a3f713f773f7b,0x3f423f4e3f583f62,0x3f7c3f783f733f6d,0x3f7e3f803f803f7f,0x3f393f2c3f1d3f0e,0x3f653f5c3f513f46,0x3e603e163d978000,0x3efc3edb3eb83e95,
0x3f753f7b3f7f3f80,0x3f463f553f623f6d,0x3ef13f0e3f223f35,0x3dc93e483e953ec4,0xbe95be48bdc90000,0xbf22bf0ebef1bec4,0xbf62bf55bf46bf35,0xbf7fbf7bbf75bf6d,
0xbe95be48bdc98000,0xbf22bf0ebef1bec4,0xbf62bf55bf46bf35,0xbf7fbf7bbf75bf6d,0xbf75bf7bbf7fbf80,0xbf46bf55bf62bf6d,0xbef1bf0ebf22bf35,0xbdc9be48be95bec4,
0xbe60beacbee6bf0e,0x3e893e163cc9bdc9,0xbf6fbf78bf7ebf80,0xbf27bf3ebf51bf62,0x3f7c3f803f7f3f7b,0x3f4a3f5c3f6a3f75,0x3f313f183efc3ec4,0x3f733f673f583f46,
0x3f7a3f713f653f55,0x3f773f7d3f803f7f,0x3eb83e793dfb8000,0x3f423f2c3f133ef1,0xbe2fbd493d973e48,0xbf1dbf04becfbe95,0x3f393f4e3f5f3f6d,0x3ea13edb3f093f22,
0xbf71bf62bf4ebf35,0xbf78bf7fbf80bf7b,0xbf2cbf46bf5cbf6d,0xbe16be95bedbbf0e,0x3f673f753f7d3f80,0x3f043f223f3e3f55,0xbd493dc93e793ec4,0xbf18bef1beacbe48,
0xbeacbef1bf18bf35,0x3e793dc9bd49be48,0x3f3e3f223f043ec4,0x3f7d3f753f673f55,0xbedbbe95be168000,0xbf5cbf46bf2cbf0e,0xbf80bf7fbf78bf6d,0xbf4ebf62bf71bf7b,
0x3d973e793ecf3f0e,0xbf13bedbbe89bdc9,0x3f7e3f803f7a3f6d,0x3f313f4e3f653f75,0x3ea13e16bcc9be48,0x3f583f3e3f1d3ef1,0xbf5fbf71bf7cbf80,0xbeb8bf04bf27bf46,
0xbf7fbf78bf6abf55,0xbf51bf67bf77bf7f,0xbdfb3d493e603ec4,0xbf39bf18bee6be95,0x3f733f7d3f803f7b,0x3f093f2c3f4a3f62,0x3efc3eac3e2f8000,0x3f6f3f5c3f423f22,
0x3f553f6d3f7b3f80,0x3e483ec43f0e3f35,0xbf0ebec4be480000,0xbf7bbf6dbf55bf35,0xbf55bf6dbf7bbf80,0xbe48bec4bf0ebf35,0x3f0e3ec43e480000,0x3f7b3f6d3f553f35,
0xbf0ebec4be488000,0xbf7bbf6dbf55bf35,0xbf55bf6dbf7bbf80,0xbe48bec4bf0ebf35,0x3f0e3ec43e488000,0x3f7b3f6d3f553f35,0x3f553f6d3f7b3f80,0x3e483ec43f0e3f35,
0x3f423f183ecf3e48,0x3f7c3f803f773f62,0xbf4abf67bf7abf80,0xbcc9be79bee6bf22,0xbf73bf5cbf39bf0e,0xbf58bf71bf7ebf7f,0x3efc3f2c3f513f6d,0xbeb8be163d973e95,
0x3f273f4e3f6a3f7b,0xbe2f3d493e893ef1,0x3f1d3edb3e608000,0x3f803f783f653f46,0xbea1bf04bf31bf55,0x3f093eac3dfbbdc9,0xbf5fbf3ebf13bec4,0xbf6fbf7dbf7fbf75,
0xbd49be95bf04bf35,0x3f4e3f223edb3e48,0x3f713f7f3f7d3f6d,0x3e793ef13f2c3f55,0x3f3e3f623f783f80,0xbe163dc93eac3f0e,0xbf67bf46bf18bec4,0xbf5cbf75bf80bf7b,
0x3f803f753f5c3f35,0x3f183f463f673f7b,0xbeacbdc93e163ec4,0xbf78bf62bf3ebf0e,0xbf2cbef1be798000,0xbf7dbf7fbf71bf55,0xbedbbf22bf4ebf6d,0x3f043e953d49be48,
0xbf09bf3ebf65bf7b,0x3efc3e79bcc9be95,0xbecfbe163dfb3ec4,0xbf7fbf71bf51bf22,0x3f7c3f673f423f0e,0x3f1d3f4e3f6f3f7f,0xbf31bf5cbf77bf80,0x3ea13d49be60bef1,
0x3f583f2c3ee63e48,0x3f5f3f783f803f75,0xbf6abf7dbf7ebf6d,0xbd97beacbf13bf46,0x3e2f3edb3f273f55,0xbf4abf18beb8bdc9,0x3f393f043e898000,0x3f733f803f7a3f62,
0x3f223f553f753f80,0xbef1be483dc93ec4,0xbf7fbf7bbf62bf35,0xbe95bf0ebf46bf6d,0x3f463f0e3e950000,0x3f623f7b3f7f3f6d,0xbdc93e483ef13f35,0xbf75bf55bf22bec4,
0xbf46bf0ebe958000,0xbf62bf7bbf7fbf6d,0x3dc9be48bef1bf35,0x3f753f553f223ec4,0x3f223f553f753f80,0xbef1be483dc93ec4,0xbf7fbf7bbf62bf35,0xbe95bf0ebf46bf6d,
0x3f6f3f803f773f55,0xbd973e793f093f46,0xbf13bf4ebf73bf80,0x3f1d3eac3cc9be95,0x3f313edb3dfbbe48,0x3f653f7d3f7c3f62,0xbf7abf5cbf27bec4,0xbefcbf3ebf6abf7f,
0xbeb8bd493e893f0e,0xbf7fbf78bf58bf22,0x3f513f183ea18000,0x3f4a3f713f803f75,0x3f393f673f7e3f7b,0xbee6be163e2f3ef1,0xbe60bf04bf42bf6d,0x3f5f3f2c3ecf3dc9,
0x3f783f7f3f673f35,0xbd493e953f183f55,0xbf7dbf62bf2cbec4,0xbeacbf22bf5cbf7b,0x3f043f463f713f80,0xbf3ebef1be163e48,0xbf4ebf75bf80bf6d,0x3edb3dc9be79bf0e,
0xbe793dc93edb3f35,0xbf80bf75bf4ebf0e,0xbe16bef1bf3ebf6d,0x3f713f463f043e48,0xbf5cbf22beac8000,0xbf2cbf62bf7dbf7b,0x3f183e95bd49bec4,0x3f673f7f3f783f55,
0x3f5f3f7d3f7a3f55,0xbecfbd493ea13f22,0xbf42bf71bf80bf6d,0x3f133e79bdfbbef1,0x3f1d3f5c3f7c3f7b,0xbf39bedbbd973e95,0xbee6bf3ebf6fbf80,0x3f583f183e89bdc9,
0xbefcbe163e603f0e,0xbf6abf80bf73bf46,0x3f273eacbcc9bec4,0x3f513f783f7e3f62,0xbf4abf04be2f3e48,0xbf31bf67bf7fbf75,0x3f653f2c3eb88000,0x3f093f4e3f773f7f,
0x3ec43f353f6d3f80,0xbf6dbf35bec40000,0xbec4bf35bf6dbf80,0x3f6d3f353ec40000,0x3ec43f353f6d3f80,0xbf6dbf35bec40000,0xbec4bf35bf6dbf80,0x3f6d3f353ec40000,
0xbf6dbf35bec48000,0xbec4bf35bf6dbf80,0x3f6d3f353ec48000,0x3ec43f353f6d3f80,0xbf6dbf35bec48000,0xbec4bf35bf6dbf80,0x3f6d3f353ec48000,0x3ec43f353f6d3f80,
0x3dfb3f043f513f7b,0xbf80bf67bf27be95,0xbea1bf2cbf6abf80,0x3f7a3f4e3efc3dc9,0xbe893e163f093f55,0xbf6fbf80bf65bf22,0x3d97beacbf31bf6d,0x3f7c3f783f4a3ef1,
0xbf7ebf5cbf13be48,0xbcc9bedbbf42bf75,0x3f733f3e3ecf8000,0x3e603f183f5f3f7f,0xbf77bf7dbf58bf0e,0x3eb8bd49bee6bf46,0x3f7f3f713f393ec4,0xbe2f3e793f1d3f62,
0xbf04bdc93eac3f35,0xbf3ebf75bf7dbf55,0x3f4e3ef13d49bec4,0x3edb3f463f783f7b,0x3e793f223f673f80,0xbf80bf62bf18be48,0x3e16be95bf2cbf6d,0x3f713f7f3f5c3f0e,
0xbf5cbf7fbf71bf35,0x3f2c3e95be16bf0e,0x3f183f623f803f6d,0xbf67bf22be793e48,0xbf78bf46bedb8000,0xbd49bef1bf4ebf7b,0x3f7d3f753f3e3ec4,0xbeac3dc93f043f55,
0xbf80bf67bf1dbe48,0x3ea1be16bf13bf62,0x3f583f043d97bec4,0x3e893f2c3f6f3f7f,0xbecf3d493efc3f55,0xbf42bf78bf7abf46,0xbe2fbf18bf65bf80,0x3f7e3f713f313e95,
0x3cc9bedbbf4abf7b,0x3f733f7d3f513ef1,0x3f093f5c3f7f3f6d,0xbf77bf3ebeb83dc9,0xbf6abf80bf5fbf0e,0x3f273e79be60bf22,0x3f7c3f4e3ee68000,0xbdfb3eac3f393f75,
0x3dc93f0e3f623f80,0xbf75bf7bbf46bec4,0x3f223e48be95bf35,0x3ef13f553f7f3f6d,0xbf7fbf55bef10000,0x3e95be48bf22bf6d,0x3f463f7b3f753f35,0xbf62bf0ebdc93ec4,
0xbf7fbf55bef18000,0x3e95be48bf22bf6d,0x3f463f7b3f753f35,0xbf62bf0ebdc93ec4,0xbdc9bf0ebf62bf80,0x3f753f7b3f463ec4,0xbf22be483e953f35,0xbef1bf55bf7fbf6d,
0xbf51bedb3d973f0e,0xbdfbbf18bf6abf7f,0xbcc9bf04bf5fbf80,0x3f653f803f583ef1,0xbe60bf2cbf73bf7b,0x3f773f783f393e95,0x3f6f3f7d3f4a3ec4,0xbf42beac3e2f3f22,
0xbf13bf67bf7fbf55,0x3f7e3f4e3ecfbdc9,0x3f803f5c3efc8000,0xbee63d493f093f62,0x3f7a3f3e3ea1be48,0xbe893e793f313f75,0xbeb83e163f1d3f6d,0xbf27bf71bf7cbf46,
0xbf2cbf75bf78bf35,0x3f7d3f463eacbe48,0xbedb3dc93f183f6d,0xbf04bf62bf80bf55,0xbd493ef13f5c3f80,0xbf4ebf7fbf67bf0e,0x3f713f223e16bec4,0xbe793e953f3e3f7b,
0x3f3e3e95be79bf35,0x3e163f223f713f7b,0xbf67bf7fbf4ebec4,0x3f5c3ef1bd49bf0e,0xbf80bf62bf048000,0x3f183dc9bedbbf55,0x3eac3f463f7d3f6d,0xbf78bf75bf2cbe48,
0x3f653f04bcc9bf0e,0xbe603eac3f4a3f7f,0x3e893f3e3f7c3f6d,0xbf6abf7dbf42be95,0xbf7fbf4ebeb83e48,0x3f133d49befcbf62,0x3dfbbedbbf58bf80,0x3f313f783f733f22,
0x3ee63f5c3f803f55,0xbf7abf71bf1dbdc9,0xbf77bf2cbe2f3ec4,0x3ecfbe16bf27bf75,0xbd97bf18bf6fbf7b,0x3f513f803f5f3ef1,0x3f7e3f673f098000,0xbf39be793ea13f46,
0xbe483ec43f553f80,0xbf0ebf6dbf7bbf35,0x3f7b3f6d3f0e0000,0xbf55bec43e483f35,0x3e48bec4bf55bf80,0x3f0e3f6d3f7b3f35,0xbf7bbf6dbf0e0000,0x3f553ec4be48bf35,
0xbf7bbf6dbf0e8000,0x3f553ec4be48bf35,0xbe483ec43f553f80,0xbf0ebf6dbf7bbf35,0x3f7b3f6d3f0e8000,0xbf55bec43e483f35,0x3e48bec4bf55bf80,0x3f0e3f6d3f7b3f35,
0xbf65bf7dbf39be48,0x3f7a3f2c3dfbbef1,0x3e89beacbf51bf80,0x3ecf3f5c3f7f3f46,0x3f273f783f6f3f0e,0xbf7cbf67befc3dc9,0xbf1dbd493f093f6d,0xbcc9bf18bf73bf75,
0x3ee6be16bf31bf7b,0x3e603f3e3f7e3f62,0x3f773f713f138000,0xbf6abf043d973f22,0xbf42be793eb83f55,0x3e2fbedbbf5fbf7f,0xbf4abf80bf58bec4,0x3f803f4e3ea1be95,
0x3f673ef1be16bf35,0xbf043dc93f2c3f7b,0xbd49bf22bf78bf6d,0x3f183f753f713f0e,0xbeac3e953f4e3f80,0xbe79bf46bf80bf55,0x3f3e3f7f3f5c3ec4,0xbf7dbf62bedb3e48,
0x3edb3f623f7d3f35,0xbf5cbf7fbf3ebe48,0x3f803f463e79bec4,0xbf4ebe953eac3f55,0xbf71bf75bf188000,0x3f783f223d49bf0e,0xbf2cbdc93f043f6d,0x3e16bef1bf67bf7b,
0xbf133d493f273f7b,0x3dfbbf04bf6fbf75,0xbf80bf4ebe893ec4,0x3f653edbbe60bf46,0xbf09bf71bf73bf0e,0x3f5f3f7d3f313dc9,0x3ecfbe79bf4abf80,0x3d973f2c3f7c3f62,
0xbf51bf80bf42be48,0x3f7e3f5c3eb8be95,0x3cc9bf18bf77bf6d,0x3ee63f673f7a3f22,0x3f583eacbea1bf55,0xbefc3e163f393f7f,0x3f6a3f783f1d8000,0xbf7fbf3ebe2f3ef1,
0xbef13e483f463f80,0x3dc9bf0ebf75bf6d,0x3e953f553f7f3f35,0xbf22bf7bbf62bec4,0x3f623f7b3f220000,0xbf7fbf55be953ec4,0x3f753f0ebdc9bf35,0xbf46be483ef13f6d,
0xbf62bf7bbf228000,0x3f7f3f553e95bec4,0xbf75bf0e3dc93f35,0x3f463e48bef1bf6d,0xbef13e483f463f80,0x3dc9bf0ebf75bf6d,0x3e953f553f7f3f35,0xbf22bf7bbf62bec4,
0xbcc9bf2cbf7ebf55,0x3ea13f5c3f7c3f22,0x3f09be16bf42bf80,0xbe893edb3f6a3f75,0xbf6fbf71befc3e48,0x3f7f3f4e3e60bef1,0xbf13bf78bf65bec4,0x3f4a3f803f393dc9,
0x3f803f3e3dfbbf0e,0xbf73bf043e2f3f46,0x3f583f7d3f278000,0xbf77bf67becf3e95,0x3eb8beacbf5fbf7b,0xbd973f183f7a3f62,0x3f513e79bee6bf6d,0xbf1d3d493f313f7f,
0x3e163f463f803f35,0xbeacbf62bf78bf0e,0x3f043f753f673ec4,0xbf2cbf7fbf4ebe48,0xbf183dc93f3e3f80,0x3edbbe95bf5cbf7b,0xbe793ef13f713f6d,0x3d49bf22bf7dbf55,
0xbf7dbf223d493f35,0x3f713ef1be79bf55,0xbf5cbe953edb3f6d,0x3f3e3dc9bf18bf7b,0xbf4ebf7fbf2c8000,0x3f673f753f04be48,0xbf78bf62beac3ec4,0x3f803f463e16bf0e,
0x3dfbbf18bf7cbf55,0xbcc93f2c3f7f3f46,0x3ea1bedbbf6fbf6d,0xbe603f043f773f62,0x3efcbe79bf58bf7b,0xbecf3eac3f653f75,0x3f27bd49bf39bf80,0xbf133e163f4a3f7f,
0x3f7e3f4e3e2fbf0e,0xbf80bf3ebd973f22,0x3f733f673eb8bec4,0xbf7abf5cbe893ef1,0x3f5f3f783f09be48,0xbf6abf71bee63e95,0x3f423f803f318000,0xbf51bf7dbf1d3dc9,
0x3f003f003f003f00,0x3f003f003f003f00,0x3f003f003f003f00,0x3f003f003f003f00,0x3f003f003f003f00,0x3f003f003f003f00,0x3f003f003f003f00,0x3f003f003f003f00,
0xbf003f00bf003f00,0xbf003f00bf003f00,0xbf003f00bf003f00,0xbf003f00bf003f00,0xbf003f00bf003f00,0xbf003f00bf003f00,0xbf003f00bf003f00,0xbf003f00bf003f00,
0xbefcbf04bf09bf0e,0xbecfbedbbee6bef1,0xbf27bf2cbf31bf35,0xbf13bf18bf1dbf22,0xbdfbbe16be2fbe48,0xbcc9bd49bd97bdc9,0xbea1beacbeb8bec4,0xbe60be79be89be95,
0x3f5f3f5c3f583f55,0x3f6a3f673f653f62,0x3f423f3e3f393f35,0x3f513f4e3f4a3f46,0x3f7e3f7d3f7c3f7b,0x3f803f803f7f3f7f,0x3f733f713f6f3f6d,0x3f7a3f783f773f75,
0xbf4ebf46bf3ebf35,0xbf67bf62bf5cbf55,0xbf78bf75bf71bf6d,0xbf80bf7fbf7dbf7b,0xbe16bdc9bd490000,0xbeacbe95be79be48,0xbf04bef1bedbbec4,0xbf2cbf22bf18bf0e,
0xbf18bf22bf2cbf35,0xbedbbef1bf04bf0e,0xbe79be95beacbec4,0xbd49bdc9be16be48,0xbf7dbf7fbf80bf80,0xbf71bf75bf78bf7b,0xbf5cbf62bf67bf6d,0xbf3ebf46bf4ebf55,
0x3eb83edb3efc3f0e,0x3d973e163e603e95,0x3f513f5c3f653f6d,0x3f1d3f2c3f393f46,0x3f803f803f7e3f7b,0x3f733f783f7c3f7f,0x3f583f4e3f423f35,0x3f773f713f6a3f62,
0xbf6fbf67bf5fbf55,0xbf7fbf7dbf7abf75,0xbf13bf04bee6bec4,0xbf4abf3ebf31bf22,0xbcc93d493dfb3e48,0xbea1be79be2fbdc9,0x3f093f183f273f35,0x3e893eac3ecf3ef1,
0xbf75bf7bbf7fbf80,0xbf46bf55bf62bf6d,0xbef1bf0ebf22bf35,0xbdc9be48be95bec4,0x3e953e483dc90000,0x3f223f0e3ef13ec4,0x3f623f553f463f35,0x3f7f3f7b3f753f6d,
0x3e953e483dc98000,0x3f223f0e3ef13ec4,0x3f623f553f463f35,0x3f7f3f7b3f753f6d,0x3f753f7b3f7f3f80,0x3f463f553f623f6d,0x3ef13f0e3f223f35,0x3dc93e483e953ec4,
0xbf09bedbbea1be48,0xbf5fbf4ebf39bf22,0x3ecf3f043f1d3f35,0xbd973d493e2f3e95,0xbf13bf2cbf42bf55,0xbdfbbe79beb8bef1,0xbf80bf7dbf77bf6d,0xbf65bf71bf7abf7f,
0xbf58bf67bf73bf7b,0xbefcbf18bf31bf46,0xbf6abf5cbf4abf35,0xbf7fbf80bf7cbf75,0x3f513f3e3f273f0e,0x3f7e3f783f6f3f62,0xbcc9be16be89bec4,0x3ee63eac3e603dc9,
0x3eac3ef13f183f35,0xbe79bdc93d493e48,0xbf3ebf22bf04bec4,0xbf7dbf75bf67bf55,0x3edb3e953e160000,0x3f5c3f463f2c3f0e,0x3f803f7f3f783f6d,0x3f4e3f623f713f7b,
0xbf71bf62bf4ebf35,0xbf78bf7fbf80bf7b,0xbf2cbf46bf5cbf6d,0xbe16be95bedbbf0e,0x3f673f753f7d3f80,0x3f043f223f3e3f55,0xbd493dc93e793ec4,0xbf18bef1beacbe48,
0x3f423f5c3f6f3f7b,0x3e2f3eac3efc3f22,0x3f4a3f2c3f093ec4,0x3f803f7d3f733f62,0xbee6bf18bf39bf55,0x3e603d49bdfbbe95,0xbf77bf67bf51bf35,0xbf6abf78bf7fbf7f,
0xbf27bf04beb8be48,0xbf7cbf71bf5fbf46,0x3f1d3f3e3f583f6d,0xbcc93e163ea13ef1,0x3f653f4e3f313f0e,0x3f7a3f803f7e3f75,0xbe89bedbbf13bf35,0x3ecf3e793d97bdc9,
0x3f553f6d3f7b3f80,0x3e483ec43f0e3f35,0xbf0ebec4be480000,0xbf7bbf6dbf55bf35,0xbf55bf6dbf7bbf80,0xbe48bec4bf0ebf35,0x3f0e3ec43e480000,0x3f7b3f6d3f553f35,
0xbf0ebec4be488000,0xbf7bbf6dbf55bf35,0xbf55bf6dbf7bbf80,0xbe48bec4bf0ebf35,0x3f0e3ec43e488000,0x3f7b3f6d3f553f35,0x3f553f6d3f7b3f80,0x3e483ec43f0e3f35,
0x3f7f3f7d3f6f3f55,0x3f133f3e3f5f3f75,0xbdfbbeacbf09bf35,0x3f313f043ea13dc9,0xbf65bf78bf80bf7b,0xbe60bedbbf1dbf46,0xbe89bd493e2f3ec4,0xbf6abf4ebf27bef1,
0xbd973e163eb83f0e,0xbf51bf2cbefcbe95,0x3f7e3f713f583f35,0x3f393f5c3f733f7f,0x3ee63e793cc9be48,0x3f7a3f673f4a3f22,0xbf77bf80bf7cbf6d,0xbecfbf18bf42bf62,
0x3f803f753f5c3f35,0x3f183f463f673f7b,0xbeacbdc93e163ec4,0xbf78bf62bf3ebf0e,0xbf2cbef1be790000,0xbf7dbf7fbf71bf55,0xbedbbf22bf4ebf6d,0x3f043e953d49be48,
0x3d493e953f043f35,0xbf4ebf22bedbbe48,0xbf71bf7fbf7dbf6d,0xbe79bef1bf2cbf55,0xbf3ebf62bf78bf80,0x3e16bdc9beacbf0e,0x3f673f463f183ec4,0x3f5c3f753f803f7b,
0x3f7a3f803f733f55,0x3e893f043f393f62,0xbeb8bf18bf4abf6d,0x3f273edb3e2fbdc9,0xbf13beacbd973e48,0xbf7ebf7dbf6abf46,0x3f803f783f5f3f35,0x3ee63f2c3f583f75,
0xbe603d493ea13f0e,0xbf77bf5cbf31bef1,0x3f6f3f4e3f1d3ec4,0x3f423f673f7c3f7f,0xbf51bf71bf7fbf7b,0x3dfbbe16becfbf22,0xbcc93e793efc3f35,0xbf65bf3ebf09be95,
0xbf22bf55bf75bf80,0x3ef13e48bdc9bec4,0x3f7f3f7b3f623f35,0x3e953f0e3f463f6d,0xbf46bf0ebe950000,0xbf62bf7bbf7fbf6d,0x3dc9be48bef1bf35,0x3f753f553f223ec4,
0x3f463f0e3e958000,0x3f623f7b3f7f3f6d,0xbdc93e483ef13f35,0xbf75bf55bf22bec4,0xbf22bf55bf75bf80,0x3ef13e48bdc9bec4,0x3f7f3f7b3f623f35,0x3e953f0e3f463f6d,
0xbecfbf2cbf5fbf7b,0x3f423f043e60bdc9,0xbe2f3e163ee63f35,0xbf7ebf67bf39bef1,0xbf80bf71bf4abf0e,0xbea1bf18bf51bf75,0x3f583f783f7f3f6d,0xbe893d493eb83f22,
0x3f6a3f3e3efc3e48,0x3f273f5c3f7a3f7f,0xbf7cbf7dbf65bf35,0xbdfbbedbbf31bf62,0xbcc9beacbf1dbf55,0x3f733f4e3f133e95,0xbf09be793d973ec4,0xbf77bf80bf6fbf46,
0x3e79bdc9bedbbf35,0x3f803f753f4e3f0e,0x3e163ef13f3e3f6d,0xbf71bf46bf04be48,0x3f5c3f223eac0000,0x3f2c3f623f7d3f7b,0xbf18be953d493ec4,0xbf67bf7fbf78bf55,
0x3f783f7f3f673f35,0xbd493e953f183f55,0xbf7dbf62bf2cbec4,0xbeacbf22bf5cbf7b,0x3f043f463f713f80,0xbf3ebef1be163e48,0xbf4ebf75bf80bf6d,0x3edb3dc9be79bf0e,
0x3f773f4e3f093e48,0x3eb83f2c3f653f7f,0xbf7fbf67bf31bec4,0xbe2fbf04bf4abf75,0x3f7e3f783f513f0e,0xbcc93eac3f273f62,0xbf73bf80bf6abf35,0x3e60be16befcbf46,
0x3e893f183f583f7b,0xbf6fbf3ebee6bdc9,0xbd97bedbbf39bf6d,0x3f7c3f5c3f1d3e95,0xbdfb3e793f133f55,0xbf80bf71bf42bef1,0x3ea1bd49becfbf35,0x3f7a3f7d3f5f3f22,
0x3ec43f353f6d3f80,0xbf6dbf35bec40000,0xbec4bf35bf6dbf80,0x3f6d3f353ec40000,0x3ec43f353f6d3f80,0xbf6dbf35bec40000,0xbec4bf35bf6dbf80,0x3f6d3f353ec40000,
0xbf6dbf35bec48000,0xbec4bf35bf6dbf80,0x3f6d3f353ec48000,0x3ec43f353f6d3f80,0xbf6dbf35bec48000,0xbec4bf35bf6dbf80,0x3f6d3f353ec48000,0x3ec43f353f6d3f80,
0xbf1dbe793e2f3f0e,0xbf39bf71bf7fbf62,0x3ee63d49beb8bf35,0x3f583f7d3f773f46,0xbf5fbf18be603e48,0xbecfbf3ebf73bf7f,0x3f423edb3cc9bec4,0x3f133f5c3f7e3f75,
0xbf4abf78bf7cbf55,0x3f313eacbd97bef1,0x3f653f803f6f3f35,0xbf09be163e893f22,0xbefcbf4ebf7abf7b,0x3f6a3f2c3ea1bdc9,0x3f273f673f803f6d,0xbf51bf04bdfb3e95,
0xbf5cbf7fbf71bf35,0x3f2c3e95be16bf0e,0x3f183f623f803f6d,0xbf67bf22be793e48,0xbf78bf46bedb0000,0xbd49bef1bf4ebf7b,0x3f7d3f753f3e3ec4,0xbeac3dc93f043f55,
0x3f043dc9beacbf35,0x3f3e3f753f7d3f55,0xbf4ebef1bd493ec4,0xbedbbf46bf78bf7b,0xbe79bf22bf67bf80,0x3f803f623f183e48,0xbe163e953f2c3f6d,0xbf71bf7fbf5cbf0e,
0x3f393eacbdfbbf0e,0x3ee63f4e3f7c3f75,0xbe603e793f273f6d,0xbf5fbf80bf6abf22,0xbeb8bf3ebf77bf7b,0x3f7f3f5c3f093dc9,0x3f513f7d3f733f35,0xbf4abedb3cc93ef1,
0x3f313f713f7e3f55,0xbf65bf18be2f3e95,0xbf7abf78bf42bec4,0x3efc3d49becfbf46,0x3f6f3f2c3e89be48,0x3d973f043f583f7f,0xbf13be163ea13f35,0xbf1dbf67bf80bf62,
0xbdc9bf0ebf62bf80,0x3f753f7b3f463ec4,0xbf22be483e953f35,0xbef1bf55bf7fbf6d,0x3f7f3f553ef10000,0xbe953e483f223f6d,0xbf46bf7bbf75bf35,0x3f623f0e3dc9bec4,
0x3f7f3f553ef18000,0xbe953e483f223f6d,0xbf46bf7bbf75bf35,0x3f623f0e3dc9bec4,0x3dc93f0e3f623f80,0xbf75bf7bbf46bec4,0x3f223e48be95bf35,0x3ef13f553f7f3f6d,
0x3f7c3f713f273e48,0xbf1dbe163eb83f46,0xbf31be793e893f35,0xbea1bf3ebf7abf75,0xbf09bd493ee63f55,0xbefcbf5cbf80bf62,0xbecfbf4ebf7ebf6d,0x3f7f3f673f133dc9,
0xbe2f3eac3f423f7b,0xbf4abf7dbf6fbf22,0xbf39bf78bf77bf35,0x3f733f2c3e60be95,0xbf58bf80bf65bf0e,0x3f5f3f043cc9bef1,0x3f6a3f183dfbbec4,0xbd973edb3f513f7f,
0xbf3ebe953e793f35,0xbe16bf22bf71bf7b,0x3f673f7f3f4e3ec4,0xbf5cbef13d493f0e,0x3f803f623f040000,0xbf18bdc93edb3f55,0xbeacbf46bf7dbf6d,0x3f783f753f2c3e48,
0xbf2cbf75bf78bf35,0x3f7d3f463eacbe48,0xbedb3dc93f183f6d,0xbf04bf62bf80bf55,0xbd493ef13f5c3f80,0xbf4ebf7fbf67bf0e,0x3f713f223e16bec4,0xbe793e953f3e3f7b,
0x3ea1be79bf39bf7b,0x3f093f673f7e3f46,0x3f5f3f803f513ec4,0xbf6fbf18bd973ef1,0xbf27be163ecf3f55,0xbe2fbf2cbf77bf75,0xbf1dbf71bf7abf35,0x3f803f5c3ee6bdc9,
0x3f733f783f313e48,0xbf58bedb3dfb3f22,0xbefc3d493f133f6d,0xbeb8bf4ebf7fbf62,0xbf42bf7dbf6abf0e,0x3f7c3f3e3e89be95,0x3f4a3eacbe60bf35,0xbcc93f043f653f7f,
0xbe483ec43f553f80,0xbf0ebf6dbf7bbf35,0x3f7b3f6d3f0e0000,0xbf55bec43e483f35,0x3e48bec4bf55bf80,0x3f0e3f6d3f7b3f35,0xbf7bbf6dbf0e0000,0x3f553ec4be48bf35,
0xbf7bbf6dbf0e8000,0x3f553ec4be48bf35,0xbe483ec43f553f80,0xbf0ebf6dbf7bbf35,0x3f7b3f6d3f0e8000,0xbf55bec43e483f35,0x3e48bec4bf55bf80,0x3f0e3f6d3f7b3f35,
0xbea1bf4ebf80bf55,0x3f583f803f4a3e95,0x3f5f3edbbe2fbf35,0xbeb83e793f423f7f,0xbd973f043f6a3f7b,0xbf13bf71bf77bf22,0xbf7ebf3ebe603ec4,0x3f313e16bee6bf62,
0x3f733f183cc9bf0e,0xbf093d493f1d3f75,0x3efc3f673f7c3f35,0xbf6fbf78bf27bdc9,0xbf7fbf5cbecf3e48,0x3f513eacbe89bf46,0xbdfbbf2cbf7abf6d,0x3f393f7d3f653ef1,
0x3edb3f623f7d3f35,0xbf5cbf7fbf3ebe48,0x3f803f463e79bec4,0xbf4ebe953eac3f55,0xbf71bf75bf180000,0x3f783f223d49bf0e,0xbf2cbdc93f043f6d,0x3e16bef1bf67bf7b,
0xbf67bef13e163f35,0x3f04bdc9bf2cbf7b,0x3d493f223f783f6d,0xbf18bf75bf71bf0e,0x3eacbe95bf4ebf80,0x3e793f463f803f55,0xbf3ebf7fbf5cbec4,0x3f7d3f623edbbe48,
0xbe2fbf3ebf7fbf55,0x3f1d3f783f6a3ef1,0x3f393e16befcbf6d,0xbea13eac3f583f7f,0x3f7a3f673ee6be48,0xbf77bf183cc93f22,0x3eb83f5c3f7e3f35,0xbf42bf80bf51be95,
0x3f7c3f2c3d97bf0e,0xbf4abe793ecf3f62,0x3f313f7d3f5f3ec4,0xbf73bf71bf093dc9,0xbe603edb3f653f7b,0xbe89bf4ebf80bf46,0xbf6fbf043dfb3f35,0x3f273d49bf13bf75,
0x3ef1be48bf46bf80,0xbdc93f0e3f753f6d,0xbe95bf55bf7fbf35,0x3f223f7b3f623ec4,0xbf62bf7bbf220000,0x3f7f3f553e95bec4,0xbf75bf0e3dc93f35,0x3f463e48bef1bf6d,
0x3f623f7b3f228000,0xbf7fbf55be953ec4,0x3f753f0ebdc9bf35,0xbf46be483ef13f6d,0x3ef1be48bf46bf80,0xbdc93f0e3f753f6d,0xbe95bf55bf7fbf35,0x3f223f7b3f623ec4,
0xbf31bd493f1d3f7b,0x3ee6be79bf51bf7f,0xbf7abf183d973f35,0x3f5f3eacbeb8bf62,0x3ecf3f673f773f0e,0xbf27bf7dbf58be95,0xbe2f3f043f733f6d,0xbdfbbf3ebf80bf46,
0xbf39bf80bf4abe48,0x3f653f783f13bdc9,0xbe60bf4ebf7fbf35,0x3efc3f713f6f3ef1,0xbf6abedb3e893f55,0x3f423e16bf09bf75,0xbf7cbf5cbea13ec4,0x3f7e3f2c3cc9bf22,
0x3f7d3f22bd49bf35,0xbf71bef13e793f55,0x3f5c3e95bedbbf6d,0xbf3ebdc93f183f7b,0x3f4e3f7f3f2c0000,0xbf67bf75bf043e48,0x3f783f623eacbec4,0xbf80bf46be163f0e,
0x3e163f463f803f35,0xbeacbf62bf78bf0e,0x3f043f753f673ec4,0xbf2cbf7fbf4ebe48,0xbf183dc93f3e3f80,0x3edbbe95bf5cbf7b,0xbe793ef13f713f6d,0x3d49bf22bf7dbf55,
0xbf1dbf7dbf51be48,0x3f313f803f423dc9,0xbee6bf71bf6abec4,0x3f093f783f5f3e95,0xbe89bf5cbf7abf0e,0x3eb83f673f733ef1,0xbd97bf3ebf80bf35,0x3e2f3f4e3f7e3f22,
0x3f4a3e16bf13bf7b,0xbf39bd493f273f7f,0x3f653eacbecfbf6d,0xbf58be793efc3f75,0x3f773f04be60bf55,0xbf6fbedb3ea13f62,0x3f7f3f2cbcc9bf35,0xbf7cbf183dfb3f46,
0xbf8000003f80,0xbf8000003f80,0xbf8000003f80,0xbf8000003f80,0xbf8000003f80,0xbf8000003f80,0xbf8000003f80,0xbf8000003f80,
0x3f808000bf808000,0x3f808000bf808000,0x3f808000bf808000,0x3f808000bf808000,0x3f808000bf808000,0x3f808000bf808000,0x3f808000bf808000,0x3f808000bf808000,
0xbe893f783e60bf7b,0xbeb83f713ea1bf75,0xbd973f803cc9bf80,0xbe2f3f7d3dfbbf7f,0xbf1d3f4e3f13bf55,0xbf313f3e3f27bf46,0xbee63f673ecfbf6d,0xbf093f5c3efcbf62,
0xbf77be793f7a3e48,0xbf6fbeac3f733e95,0xbf7fbd493f808000,0xbf7cbe163f7e3dc9,0xbf4abf183f513f0e,0xbf39bf2c3f423f22,0xbf65bedb3f6a3ec4,0xbf58bf043f5f3ef1,
0x3f4ebf22bf3e3f35,0x3f67bef1bf5c3f0e,0x3f78be95bf713ec4,0x3f80bdc9bf7d3e48,0x3e16bf7fbd493f80,0x3eacbf75be793f7b,0x3f04bf62bedb3f6d,0x3f2cbf46bf183f55,
0x3f183f46bf2cbf35,0x3edb3f62bf04bf55,0x3e793f75beacbf6d,0x3d493f7fbe16bf7b,0x3f7d3dc9bf808000,0x3f713e95bf78be48,0x3f5c3ef1bf67bec4,0x3f3e3f22bf4ebf0e,
0xbf6abeac3f773e48,0xbf42bf183f583ef1,0xbf7c3e793f73bec4,0xbf7ebd493f80bdc9,0xbf393f3e3f1dbf55,0xbf653f043f51bf22,0xbe603f7d3d97bf80,0xbefc3f673eb8bf75,
0x3ecfbf71be893f7b,0x3f27bf4ebf093f62,0xbe2fbf783ea13f6d,0x3dfbbf803cc93f7f,0xbf31bf2c3f4a3f0e,0xbee6bf5c3f133f46,0xbf7abe163f7f8000,0xbf5fbedb3f6f3e95,
0x3e95bf7bbdc93f80,0x3f22bf55bef13f6d,0x3f62bf0ebf463f35,0x3f7fbe48bf753ec4,0x3f753e48bf7f0000,0x3f463f0ebf62bec4,0x3ef13f55bf22bf35,0x3dc93f7bbe95bf6d,
0x3f753e48bf7f8000,0x3f463f0ebf62bec4,0x3ef13f55bf22bf35,0x3dc93f7bbe95bf6d,0xbe953f7b3dc9bf80,0xbf223f553ef1bf6d,0xbf623f0e3f46bf35,0xbf7f3e483f75bec4,
0xbf7a3eac3f65bf0e,0xbf77be163f80bdc9,0xbeb83f783dfbbf80,0xbf423f3e3f13bf62,0x3e2fbf803d973f7b,0x3f1dbf5cbecf3f75,0xbf39bf183f5f3ec4,0xbea1bf673f093f46,
0xbe60bf713ee63f55,0x3e89bf7dbcc93f7f,0xbf6fbe793f7e8000,0xbf27bf2c3f513ef1,0x3f7c3d49bf7f3e48,0x3f4a3f04bf6abe95,0x3f31bf4ebefc3f6d,0x3f73bedbbf583f22,
0x3eac3f62bf18bf35,0xbe793f7fbd49bf7b,0xbf3e3f463f04bf6d,0xbf7d3e953f67bf0e,0x3edbbf75be163f80,0x3f5cbf22bf2c3f55,0x3f80bdc9bf783ec4,0x3f4e3ef1bf71be48,
0xbf713ef13f4ebf35,0xbf78bdc93f80be48,0xbf2cbf223f5c3ec4,0xbe16bf753edb3f55,0x3f673e95bf7d8000,0x3f043f46bf3ebf0e,0xbd493f7fbe79bf6d,0xbf183f623eacbf7b,
0x3f7fbe79bf6a3f0e,0x3f513edbbf77bdc9,0x3dfbbf803e603f6d,0x3f39bf4ebee63f75,0xbf73be163f80be48,0xbf09bf3e3f4a3ef1,0xbefc3f713e2fbf80,0xbf6f3f043f42bf46,
0x3d973f78becfbf55,0xbf133f673e89bf7f,0x3f7ebd49bf7a3ec4,0x3f313f18bf65be95,0x3ea1bf7d3cc93f7b,0x3f58bf2cbf1d3f62,0xbf5fbeac3f7c8000,0xbeb8bf5c3f273f22,
0x3f0ebf6dbe483f80,0x3f7bbec4bf553f35,0x3f553ec4bf7b0000,0x3e483f6dbf0ebf35,0xbf0e3f6d3e48bf80,0xbf7b3ec43f55bf35,0xbf55bec43f7b0000,0xbe48bf6d3f0e3f35,
0x3f553ec4bf7b8000,0x3e483f6dbf0ebf35,0xbf0e3f6d3e48bf80,0xbf7b3ec43f55bf35,0xbf55bec43f7b8000,0xbe48bf6d3f0e3f35,0x3f0ebf6dbe483f80,0x3f7bbec4bf553f35,
0xbf27bf183f6a3e48,0x3e2fbf803e893f62,0xbf1d3f673e60bf80,0xbf803e793f65bf22,0x3ea13f5cbf31bf0e,0xbf093f713dfbbf7f,0x3f5fbf2cbf133f6d,0x3f6f3e16bf7f3e95,
0x3f42bf4ebecf3f7b,0x3f7cbd49bf773ef1,0xbf4abedb3f7a8000,0xbcc9bf783ee63f46,0xbf733f043f39bf55,0xbf58beac3f7ebdc9,0x3efc3f3ebf51bec4,0xbeb83f7dbd97bf75,
0xbf803e953f5cbf35,0xbf18bf223f673e48,0x3eacbf7f3e163f6d,0x3f78bef1bf3e3f55,0x3f2cbf62be793f80,0x3f7dbdc9bf713f0e,0x3edb3f46bf4ebec4,0xbf043f753d49bf7b,
0xbd49bf753f043f35,0x3f4ebf46bedb3f7b,0x3f713dc9bf7d3ec4,0x3e793f62bf2cbf0e,0x3f3e3ef1bf788000,0xbe163f7fbeacbf55,0xbf673f223f18bf6d,0xbf5cbe953f80be48,
0xbf583f3e3ee6bf7b,0xbf5fbe793f80be95,0x3f6a3e16bf7e3ec4,0x3d973f71bf13bf22,0xbe2fbf673f273f0e,0x3f4abf4ebeb83f7f,0xbf393f5c3e89bf80,0xbf73bd493f7abef1,
0xbf09bf2c3f653e48,0x3efcbf783cc93f75,0xbecf3f7dbdfbbf6d,0xbf7f3eac3f51bf46,0x3f7cbedbbf423f55,0x3f1d3f18bf6fbdc9,0xbf31bf043f778000,0x3ea1bf803e603f62,
0x3f46bf55be953f80,0x3f623e48bf7f3ec4,0xbdc93f7bbef1bf35,0xbf753f0e3f22bf6d,0xbf22bf0e3f750000,0x3ef1bf7b3dc93f6d,0x3f7fbe48bf623f35,0x3e953f55bf46bec4,
0x3f223f0ebf758000,0xbef13f7bbdc9bf6d,0xbf7f3e483f62bf35,0xbe95bf553f463ec4,0x3f46bf55be953f80,0x3f623e48bf7f3ec4,0xbdc93f7bbef1bf35,0xbf753f0e3f22bf6d,
0x3eb8bf803e893f55,0x3f7fbe79bf583f46,0xbf513f4e3ea1bf80,0xbf4abeac3f80be95,0xbf39bedb3f7ebe48,0x3ee6bf7d3e2f3f62,0x3e603f5cbf42bec4,0xbf5f3f3e3ecfbf7f,
0x3f6f3d49bf773f0e,0xbd973f78bf09bf22,0xbf13bf183f738000,0x3f1dbf71bcc93f75,0x3f31bf67bdfb3f7b,0x3f653e16bf7c3ef1,0xbf7a3f043f27bf6d,0xbefcbf2c3f6a3dc9,
0x3e79bf7f3edb3f35,0x3f80be95bf4e3f55,0x3e163f62bf3ebec4,0xbf713f223f04bf7b,0x3f5cbf46beac3f80,0x3f2c3ef1bf7d3e48,0xbf183f75bd49bf6d,0xbf67bdc93f78bf0e,
0x3f78bdc9bf673f35,0xbd493f75bf18bf0e,0xbf7d3ef13f2cbf6d,0xbeacbf463f5c3e48,0x3f043f22bf718000,0xbf3e3f623e16bf7b,0xbf4ebe953f80bec4,0x3edbbf7f3e793f55,
0x3efcbf7d3e603f55,0x3f6a3d49bf733f22,0xbf273f71bcc9bf6d,0xbf51be793f7ebef1,0x3f4abf5cbe2f3f7b,0x3f313edbbf7f3e95,0xbf653f3e3eb8bf80,0xbf09bf183f77bdc9,
0x3f5f3e16bf7a3f0e,0xbecf3f80bea1bf46,0xbf42beac3f80bec4,0x3f13bf783dfb3f62,0x3f1d3f04bf7c3e48,0xbf393f673d97bf75,0xbee6bf2c3f6f8000,0x3f58bf4ebe893f7f,
0x3f6dbf35bec43f80,0x3ec43f35bf6d0000,0xbf6d3f353ec4bf80,0xbec4bf353f6d0000,0x3f6dbf35bec43f80,0x3ec43f35bf6d0000,0xbf6d3f353ec4bf80,0xbec4bf353f6d0000,
0x3ec43f35bf6d8000,0xbf6d3f353ec4bf80,0xbec4bf353f6d8000,0x3f6dbf35bec43f80,0x3ec43f35bf6d8000,0xbf6d3f353ec4bf80,0xbec4bf353f6d8000,0x3f6dbf35bec43f80,
0x3f7ebf04bf133f7b,0x3cc93f67bf42be95,0xbf733f2c3ecfbf80,0xbe60bf4e3f5f3dc9,0x3f77be16bf583f55,0xbeb83f80bee6bf22,0xbf7f3eac3f39bf6d,0x3e2fbf783f1d3ef1,
0x3dfb3f5cbf51be48,0xbf803edb3f27bf75,0xbea1bf3e3f6a8000,0x3f7abf18befc3f7f,0xbe893f7dbf09bf0e,0xbf6f3d493f65bf46,0x3d97bf713f313ec4,0x3f7cbe79bf4a3f62,
0x3f5c3dc9bf713f35,0xbf2c3f75be16bf55,0xbf18bef13f80bec4,0x3f67bf46be793f7b,0x3f78bf22bedb3f80,0x3d493f62bf4ebe48,0xbf7d3e953f3ebf6d,0x3eacbf7f3f043f0e,
0xbf043f7fbeacbf35,0xbf3ebe953f7dbf0e,0x3f4ebf62bd493f6d,0x3edb3f22bf783e48,0x3e793f46bf678000,0xbf803ef13f18bf7b,0x3e16bf753f2c3ec4,0x3f71bdc9bf5c3f55,
0xbcc93f67bf4abe48,0xbf733e163f51bf62,0xbf09bf043f7fbec4,0x3f77bf2cbeb83f7f,0x3f6abd49bf5f3f55,0xbf273f78be60bf46,0xbf7c3f183ee6bf80,0x3dfbbf713f393e95,
0xbf803edb3f1dbf7b,0x3ea1bf7d3f133ef1,0x3f58bf5cbd973f6d,0x3e893f3ebf6f3dc9,0xbecf3f80befcbf0e,0xbf42be793f7abf22,0xbe2fbf4e3f658000,0x3f7ebeacbf313f75,
0x3f7fbf0ebef13f80,0xbe953f7bbf22bec4,0xbf46be483f75bf35,0x3f62bf55bdc93f6d,0x3dc93f55bf620000,0xbf753e483f46bf6d,0x3f22bf7b3e953f35,0x3ef13f0ebf7f3ec4,
0x3dc93f55bf628000,0xbf753e483f46bf6d,0x3f22bf7b3e953f35,0x3ef13f0ebf7f3ec4,0xbf7f3f0e3ef1bf80,0x3e95bf7b3f223ec4,0x3f463e48bf753f35,0xbf623f553dc9bf6d,
0x3f133edbbf7f3f0e,0xbf7e3f183ecfbf7f,0xbf803f043efcbf80,0x3ee6bf803f093ef1,0xbf7a3f2c3ea1bf7b,0x3e89bf783f313e95,0x3eb8bf7d3f1d3ec4,0x3f273eacbf7c3f22,
0xbf513f67bd97bf55,0xbdfbbf4e3f6abdc9,0xbcc9bf5c3f5f8000,0x3f65bd49bf583f62,0xbe60bf3e3f73be48,0x3f77be79bf393f75,0x3f6fbe16bf4a3f6d,0xbf423f71be2fbf46,
0xbf3e3f75be79bf35,0xbe16bf463f71be48,0x3f67bdc9bf4e3f6d,0xbf5c3f62bd49bf55,0x3f80bef1bf043f80,0xbf183f7fbedbbf0e,0xbeacbf223f7dbec4,0x3f78be95bf2c3f7b,
0xbf2cbe953f78bf35,0x3f7dbf22beac3f7b,0xbedb3f7fbf18bec4,0xbf04bef13f80bf0e,0xbd493f62bf5c8000,0xbf4ebdc93f67bf55,0x3f71bf46be163f6d,0xbe793f75bf3ebe48,
0xbee6bf043f80bf0e,0x3f7abeacbf1d3f7f,0x3f77bf3ebe2f3f6d,0xbecf3f7dbf27be95,0x3d973f4ebf6f3e48,0xbf51bd493f5fbf62,0xbf7e3edb3f09bf80,0x3f39bf783ea13f22,
0x3f65bf5c3cc93f55,0xbe603f71bf4abdc9,0x3e893f2cbf7c3ec4,0xbf6a3e163f42bf75,0xbf7f3f183eb8bf7b,0x3f13bf803efc3ef1,0x3dfbbf673f588000,0x3f313e79bf733f46,
0x3f7bbec4bf0e3f80,0xbf553f6dbe48bf35,0x3e48bf6d3f550000,0x3f0e3ec4bf7b3f35,0xbf7b3ec43f0ebf80,0x3f55bf6d3e483f35,0xbe483f6dbf550000,0xbf0ebec43f7bbf35,
0xbe483f6dbf558000,0xbf0ebec43f7bbf35,0x3f7bbec4bf0e3f80,0xbf553f6dbe48bf35,0x3e48bf6d3f558000,0x3f0e3ec4bf7b3f35,0xbf7b3ec43f0ebf80,0x3f55bf6d3e483f35,
0xbee63f7dbf31be48,0xbe60bf2c3f7ebef1,0xbf773eac3f13bf80,0x3f6abf5c3d973f46,0x3f42bf783eb83f0e,0xbe2f3f67bf5f3dc9,0x3f4a3d49bf583f6d,0xbf803f183ea1bf75,
0xbf653e163f39bf7b,0x3f7abf3ebdfb3f62,0x3e89bf713f518000,0x3ecf3f04bf7f3f22,0x3f273e79bf6f3f55,0xbf7c3edb3efcbf7f,0xbf1d3f80bf09bec4,0xbcc9bf4e3f73be95,
0xbedbbef13f7dbf35,0x3f5cbdc9bf3e3f7b,0xbf803f223e79bf6d,0x3f4ebf753eac3f0e,0x3f71be95bf183f80,0xbf783f463d49bf55,0x3f2cbf7f3f043ec4,0xbe163f62bf673e48,
0x3f67bf623e163f35,0xbf043f7fbf2cbe48,0xbd49bf463f78bec4,0x3f183e95bf713f55,0xbeac3f75bf4e8000,0xbe79bf223f80bf0e,0x3f3e3dc9bf5c3f6d,0xbf7d3ef13edbbf7b,
0x3f51bd49bf423f7b,0xbf7e3f043eb8bf75,0xbcc93f4ebf773ec4,0xbee6bedb3f7abf46,0xbf583f71bea1bf0e,0x3efcbf7d3f393dc9,0xbf6a3e793f1dbf80,0x3f7fbf2cbe2f3f62,
0xbf133f80bf27be48,0x3dfbbf5c3f6fbe95,0xbf803f183e89bf6d,0x3f65bf673e603f22,0xbf09beac3f73bf55,0x3f5fbe16bf313f7f,0x3ecfbf783f4a8000,0x3d973f3ebf7c3ef1,
0x3f62be48bf223f80,0xbf7f3f0e3e95bf6d,0x3f75bf553dc93f35,0xbf463f7bbef1bec4,0x3ef1bf7b3f460000,0xbdc93f55bf753ec4,0xbe95bf0e3f7fbf35,0x3f223e48bf623f6d,
0xbef13f7bbf468000,0x3dc9bf553f75bec4,0x3e953f0ebf7f3f35,0xbf22be483f62bf6d,0x3f62be48bf223f80,0xbf7f3f0e3e95bf6d,0x3f75bf553dc93f35,0xbf463f7bbef1bec4,
0xbf803f2c3dfbbf55,0x3f73bf5c3e2f3f22,0xbf583e163f27bf80,0x3f77bedbbecf3f75,0xbeb83f71bf5f3e48,0x3d97bf4e3f7abef1,0xbf513f78bee6bec4,0x3f1dbf803f313dc9,
0xbcc9bf3e3f7ebf0e,0x3ea13f04bf7c3f46,0x3f09bf7d3f428000,0xbe893f67bf6a3e95,0xbf6f3eac3efcbf7b,0x3f7fbf18be603f62,0xbf13be793f65bf6d,0x3f4abd49bf393f7f,
0x3f7dbf463d493f35,0xbf713f62be79bf0e,0x3f5cbf753edb3ec4,0xbf3e3f7fbf18be48,0x3f4ebdc9bf2c3f80,0xbf673e953f04bf7b,0x3f78bef1beac3f6d,0xbf803f223e16bf55,
0x3e163f22bf803f35,0xbeacbef13f78bf55,0x3f043e95bf673f6d,0xbf2cbdc93f4ebf7b,0xbf183f7fbf3e8000,0x3edbbf753f5cbe48,0xbe793f62bf713ec4,0x3d49bf463f7dbf0e,
0xbf7e3f183e2fbf55,0x3f80bf2cbd973f46,0xbf733edb3eb8bf6d,0x3f7abf04be893f62,0xbf5f3e793f09bf7b,0x3f6abeacbee63f75,0xbf423d493f31bf80,0x3f51be16bf1d3f7f,
0x3dfbbf4e3f7cbf0e,0xbcc93f3ebf7f3f22,0x3ea1bf673f6fbec4,0xbe603f5cbf773ef1,0x3efcbf783f58be48,0xbecf3f71bf653e95,0x3f27bf803f398000,0xbf133f7dbf4a3dc9,
0xbf8000003f80,0xbf8000003f80,0xbf8000003f80,0xbf8000003f80,0xbf8000003f80,0xbf8000003f80,0xbf8000003f80,0xbf8000003f80,
0x3f808000bf808000,0x3f808000bf808000,0x3f808000bf808000,0x3f808000bf808000,0x3f808000bf808000,0x3f808000bf808000,0x3f808000bf808000,0x3f808000bf808000,
0xbf5f3f043f58bf0e,0xbf6a3edb3f65bef1,0xbf423f2c3f39bf35,0xbf513f183f4abf22,0xbf7e3e163f7cbe48,0xbf803d493f7fbdc9,0xbf733eac3f6fbec4,0xbf7a3e793f77be95,
0xbefcbf5c3f093f55,0xbecfbf673ee63f62,0xbf27bf3e3f313f35,0xbf13bf4e3f1d3f46,0xbdfbbf7d3e2f3f7b,0xbcc9bf803d973f7f,0xbea1bf713eb83f6d,0xbe60bf783e893f75,
0x3f183f46bf2cbf35,0x3edb3f62bf04bf55,0x3e793f75beacbf6d,0x3d493f7fbe16bf7b,0x3f7d3dc9bf800000,0x3f713e95bf78be48,0x3f5c3ef1bf67bec4,0x3f3e3f22bf4ebf0e,
0xbf4e3f223f3ebf35,0xbf673ef13f5cbf0e,0xbf783e953f71bec4,0xbf803dc93f7dbe48,0xbe163f7f3d49bf80,0xbeac3f753e79bf7b,0xbf043f623edbbf6d,0xbf2c3f463f18bf55,
0x3f6fbedbbf5f3f0e,0x3f7fbe16bf7a3e95,0x3f13bf5cbee63f6d,0x3f4abf2cbf313f46,0x3cc9bf803dfb3f7b,0x3ea1bf78be2f3f7f,0xbf09bf4e3f273f35,0xbe89bf713ecf3f62,
0x3eb83f67befcbf55,0x3d973f7dbe60bf75,0x3f513f04bf65bec4,0x3f1d3f3ebf39bf22,0x3f80bd49bf7e3e48,0x3f733e79bf7cbdc9,0x3f58bf18bf423f35,0x3f77beacbf6a3ef1,
0xbe953f7b3dc9bf80,0xbf223f553ef1bf6d,0xbf623f0e3f46bf35,0xbf7f3e483f75bec4,0xbf75be483f7f0000,0xbf46bf0e3f623ec4,0xbef1bf553f223f35,0xbdc9bf7b3e953f6d,
0xbf75be483f7f8000,0xbf46bf0e3f623ec4,0xbef1bf553f223f35,0xbdc9bf7b3e953f6d,0x3e95bf7bbdc93f80,0x3f22bf55bef13f6d,0x3f62bf0ebf463f35,0x3f7fbe48bf753ec4,
0x3f583edbbf73be48,0x3efc3f4ebf31bf22,0x3f6abf04bf4a3f35,0x3f7fbd49bf7c3e95,0xbf513f2c3f27bf55,0xbf7e3e793f6fbef1,0x3cc93f7dbe89bf6d,0xbee63f713e60bf7f,
0xbf093f673ea1bf7b,0xbf5f3f183f39bf46,0x3ecf3f5cbf1dbf35,0xbd973f80be2fbf75,0xbf13bf3e3f423f0e,0xbdfbbf783eb83f62,0xbf803e163f77bec4,0xbf65beac3f7a3dc9,
0x3f71bef1bf4e3f35,0x3f783dc9bf803e48,0x3f2c3f22bf5cbec4,0x3e163f75bedbbf55,0xbf67be953f7d0000,0xbf04bf463f3e3f0e,0x3d49bf7f3e793f6d,0x3f18bf62beac3f7b,
0x3eac3f62bf18bf35,0xbe793f7fbd49bf7b,0xbf3e3f463f04bf6d,0xbf7d3e953f67bf0e,0x3edbbf75be163f80,0x3f5cbf22bf2c3f55,0x3f80bdc9bf783ec4,0x3f4e3ef1bf71be48,
0x3f27bf5cbeb83f7b,0x3f7cbeacbf5f3f22,0xbf1dbf2c3f583ec4,0x3cc9bf7d3ea13f62,0xbf653f183f31bf55,0xbf7abd493f7ebe95,0x3e893f67bf13bf35,0xbecf3f783d97bf7f,
0x3f423f04bf6fbe48,0x3e2f3f71befcbf46,0x3f4abf3ebf093f6d,0x3f80be16bf733ef1,0xbee6bf4e3f393f0e,0x3e60bf803dfb3f75,0xbf773edb3f51bf35,0xbf6abe793f7fbdc9,
0x3f0ebf6dbe483f80,0x3f7bbec4bf553f35,0x3f553ec4bf7b0000,0x3e483f6dbf0ebf35,0xbf0e3f6d3e48bf80,0xbf7b3ec43f55bf35,0xbf55bec43f7b0000,0xbe48bf6d3f0e3f35,
0x3f553ec4bf7b8000,0x3e483f6dbf0ebf35,0xbf0e3f6d3e48bf80,0xbf7b3ec43f55bf35,0xbf55bec43f7b8000,0xbe48bf6d3f0e3f35,0x3f0ebf6dbe483f80,0x3f7bbec4bf553f35,
0x3d97bf7d3eb83f55,0x3f51bf3ebefc3f75,0xbf7e3eac3f58bf35,0xbf39bf043f733dc9,0xbee63f783cc9bf7b,0xbf7a3edb3f4abf46,0x3f773d49bf7c3ec4,0x3ecf3f4ebf42bef1,
0x3f7fbe16bf6f3f0e,0x3f133f2cbf5fbe95,0xbdfbbf713f093f35,0x3f31bf5cbea13f7f,0xbf65be793f80be48,0xbe60bf673f1d3f22,0xbe893f80be2fbf6d,0xbf6a3f183f27bf62,
0xbd49bf753f043f35,0x3f4ebf46bedb3f7b,0x3f713dc9bf7d3ec4,0x3e793f62bf2cbf0e,0x3f3e3ef1bf780000,0xbe163f7fbeacbf55,0xbf673f223f18bf6d,0xbf5cbe953f80be48,
0x3f80be95bf5c3f35,0x3f183f22bf67be48,0xbeac3f7fbe16bf6d,0xbf783ef13f3ebf55,0xbf2c3f623e79bf80,0xbf7d3dc93f71bf0e,0xbedbbf463f4e3ec4,0x3f04bf75bd493f7b,
0x3e60bf803ea13f55,0x3f77bf04bf313f62,0xbf6f3f183f1dbf6d,0xbf42bedb3f7cbdc9,0x3f513eacbf7f3e48,0xbdfb3f7dbecfbf46,0x3cc9bf783efc3f35,0x3f65bf2cbf093f75,
0x3f7abd49bf733f0e,0x3e893f5cbf39bef1,0xbeb8bf4e3f4a3ec4,0x3f27bf67be2f3f7f,0xbf133f713d97bf7b,0xbf7e3e163f6abf22,0x3f80be79bf5f3f35,0x3ee63f3ebf58be95,
0xbf463f553e95bf80,0xbf62be483f7fbec4,0x3dc9bf7b3ef13f35,0x3f75bf0ebf223f6d,0x3f223f0ebf750000,0xbef13f7bbdc9bf6d,0xbf7f3e483f62bf35,0xbe95bf553f463ec4,
0xbf22bf0e3f758000,0x3ef1bf7b3dc93f6d,0x3f7fbe48bf623f35,0x3e953f55bf46bec4,0xbf463f553e95bf80,0xbf62be483f7fbec4,0x3dc9bf7b3ef13f35,0x3f75bf0ebf223f6d,
0xbf6a3f2c3efcbf7b,0xbf27bf043f7abdc9,0x3f7cbe16bf653f35,0x3dfb3f67bf31bef1,0x3cc93f71bf1dbf0e,0xbf733f183f13bf75,0x3f09bf783d973f6d,0x3f77bd49bf6f3f22,
0xbecfbf3e3f5f3e48,0x3f42bf5cbe603f7f,0xbe2f3f7dbee6bf35,0xbf7e3edb3f39bf62,0xbf803eac3f4abf55,0xbea1bf4e3f513e95,0x3f583e79bf7f3ec4,0xbe893f80beb8bf46,
0xbf783dc93f67bf35,0x3d49bf753f183f0e,0x3f7dbef1bf2c3f6d,0x3eac3f46bf5cbe48,0xbf04bf223f710000,0x3f3ebf62be163f7b,0x3f4e3e95bf803ec4,0xbedb3f7fbe79bf55,
0x3e79bf7f3edb3f35,0x3f80be95bf4e3f55,0x3e163f62bf3ebec4,0xbf713f223f04bf7b,0x3f5cbf46beac3f80,0x3f2c3ef1bf7d3e48,0xbf183f75bd49bf6d,0xbf67bdc93f78bf0e,
0xbe89bf4e3f583e48,0x3f6fbf2cbee63f7f,0x3d973f67bf39bec4,0xbf7c3f043f1dbf75,0x3dfbbf783f133f0e,0x3f80beacbf423f62,0xbea13f80becfbf35,0xbf7a3e163f5fbf46,
0x3f77bf18bf093f7b,0x3eb83f3ebf65bdc9,0xbf7f3edb3f31bf6d,0xbe2fbf5c3f4a3e95,0x3f7ebe79bf513f55,0xbcc93f71bf27bef1,0xbf733d493f6abf35,0x3e60bf7d3efc3f22,
0x3f6dbf35bec43f80,0x3ec43f35bf6d0000,0xbf6d3f353ec4bf80,0xbec4bf353f6d0000,0x3f6dbf35bec43f80,0x3ec43f35bf6d0000,0xbf6d3f353ec4bf80,0xbec4bf353f6d0000,
0x3ec43f35bf6d8000,0xbf6d3f353ec4bf80,0xbec4bf353f6d8000,0x3f6dbf35bec43f80,0x3ec43f35bf6d8000,0xbf6d3f353ec4bf80,0xbec4bf353f6d8000,0x3f6dbf35bec43f80,
0x3f4a3e79bf7c3f0e,0xbf313f71bd97bf62,0xbf65bd493f6fbf35,0x3f09bf7d3e893f46,0x3efc3f18bf7a3e48,0xbf6a3f3e3ea1bf7f,0xbf27bedb3f80bec4,0x3f51bf5cbdfb3f75,
0xbf1d3f78be2fbf55,0xbf39beac3f7fbef1,0x3ee6bf803eb83f35,0x3f583e16bf773f22,0xbf5f3f4e3e60bf7b,0xbecfbf2c3f73bdc9,0x3f42bf67bcc93f6d,0x3f133f04bf7e3e95,
0xbf043f7fbeacbf35,0xbf3ebe953f7dbf0e,0x3f4ebf62bd493f6d,0x3edb3f22bf783e48,0x3e793f46bf670000,0xbf803ef13f18bf7b,0x3e16bf753f2c3ec4,0x3f71bdc9bf5c3f55,
0xbf5cbdc93f71bf35,0x3f2cbf753e163f55,0x3f183ef1bf803ec4,0xbf673f463e79bf7b,0xbf783f223edbbf80,0xbd49bf623f4e3e48,0x3f7dbe95bf3e3f6d,0xbeac3f7fbf04bf0e,
0xbf31beac3f7ebf0e,0x3f65bf4ebe2f3f75,0x3f7abe79bf423f6d,0xbefc3f80becfbf22,0xbf6f3f3e3e89bf7b,0xbd97bf5c3f583dc9,0x3f13bf7d3ea13f35,0x3f1d3edbbf803ef1,
0x3f39bf713dfb3f55,0x3ee63f18bf7c3e95,0xbe603f78bf27bec4,0xbf5fbd493f6abf46,0xbeb8bf2c3f77be48,0x3f7fbf04bf093f7f,0x3f513e16bf733f35,0xbf4a3f67bcc9bf62,
0xbf7f3f0e3ef1bf80,0x3e95bf7b3f223ec4,0x3f463e48bf753f35,0xbf623f553dc9bf6d,0xbdc9bf553f620000,0x3f75be48bf463f6d,0xbf223f7bbe95bf35,0xbef1bf0e3f7fbec4,
0xbdc9bf553f628000,0x3f75be48bf463f6d,0xbf223f7bbe95bf35,0xbef1bf0e3f7fbec4,0x3f7fbf0ebef13f80,0xbe953f7bbf22bec4,0xbf46be483f75bf35,0x3f62bf55bdc93f6d,
0x3e2fbf713f423e48,0x3f4a3e16bf6f3f46,0x3f393e79bf773f35,0xbf733f3e3e60bf75,0x3f583d49bf653f55,0xbf5f3f5c3cc9bf62,0xbf6a3f4e3dfbbf6d,0x3d97bf673f513dc9,
0x3f7cbeacbf273f7b,0xbf1d3f7dbeb8bf22,0xbf313f78be89bf35,0xbea1bf2c3f7abe95,0xbf093f80bee6bf0e,0xbefcbf043f80bef1,0xbecfbf183f7ebec4,0x3f7fbedbbf133f7f,
0x3f2c3e95bf783f35,0xbf7d3f223eacbf7b,0x3edbbf7f3f183ec4,0x3f043ef1bf803f0e,0x3d49bf623f5c0000,0x3f4e3dc9bf673f55,0xbf713f463e16bf6d,0x3e79bf753f3e3e48,
0xbf3e3f75be79bf35,0xbe16bf463f71be48,0x3f67bdc9bf4e3f6d,0xbf5c3f62bd49bf55,0x3f80bef1bf043f80,0xbf183f7fbedbbf0e,0xbeacbf223f7dbec4,0x3f78be95bf2c3f7b,
0xbf733e793f31bf7b,0x3f58bf673dfb3f46,0x3efcbf803f133ec4,0x3eb83f18bf7f3ef1,0x3f423e16bf6a3f55,0xbf7c3f2c3e89bf75,0xbf4a3f71be60bf35,0x3cc9bf5c3f65bdc9,
0x3ea1bf783f393e48,0x3f093edbbf7e3f22,0x3f5fbd49bf513f6d,0xbf6f3f4e3d97bf62,0xbf273f7dbecfbf0e,0xbe2fbf3e3f77be95,0xbf1dbeac3f7abf35,0x3f80bf04bee63f7f,
0x3f7bbec4bf0e3f80,0xbf553f6dbe48bf35,0x3e48bf6d3f550000,0x3f0e3ec4bf7b3f35,0xbf7b3ec43f0ebf80,0x3f55bf6d3e483f35,0xbe483f6dbf550000,0xbf0ebec43f7bbf35,
0xbe483f6dbf558000,0xbf0ebec43f7bbf35,0x3f7bbec4bf0e3f80,0xbf553f6dbe48bf35,0x3e48bf6d3f558000,0x3f0e3ec4bf7b3f35,0xbf7b3ec43f0ebf80,0x3f55bf6d3e483f35,
0xbf733f4e3cc9bf55,0x3f09bf803f1d3e95,0xbefcbedb3f7cbf35,0x3f6fbe79bf273f7f,0x3f7fbf04becf3f7b,0xbf513f71be89bf22,0x3dfb3f3ebf7a3ec4,0xbf39be163f65bf62,
0xbea1bf183f80bf0e,0x3f58bd49bf4a3f75,0x3f5fbf673e2f3f35,0xbeb83f78bf42bdc9,0xbd973f5cbf6a3e48,0xbf13beac3f77bf46,0xbf7e3f2c3e60bf6d,0x3f31bf7d3ee63ef1,
0x3f67bf623e163f35,0xbf043f7fbf2cbe48,0xbd49bf463f78bec4,0x3f183e95bf713f55,0xbeac3f75bf4e0000,0xbe79bf223f80bf0e,0x3f3e3dc9bf5c3f6d,0xbf7d3ef13edbbf7b,
0x3edb3ef1bf7d3f35,0xbf5c3dc93f3ebf7b,0x3f80bf22be793f6d,0xbf4e3f75beacbf0e,0xbf713e953f18bf80,0x3f78bf46bd493f55,0xbf2c3f7fbf04bec4,0x3e16bf623f67be48,
0xbf7c3f3e3d97bf55,0x3f4abf783ecf3ef1,0xbf31be163f5fbf6d,0x3f73beacbf093f7f,0x3e60bf673f65be48,0x3e893f18bf803f22,0x3f6fbf5c3dfb3f35,0xbf273f80bf13be95,
0xbe2fbf2c3f7fbf0e,0x3f1d3e79bf6a3f62,0x3f39bf7d3efc3ec4,0xbea13f71bf583dc9,0x3f7abedbbee63f7b,0xbf773f4ebcc9bf46,0x3eb83f04bf7e3f35,0xbf42bd493f51bf75,
0xbf623e483f22bf80,0x3f7fbf0ebe953f6d,0xbf753f55bdc9bf35,0x3f46bf7b3ef13ec4,0xbef13f7bbf460000,0x3dc9bf553f75bec4,0x3e953f0ebf7f3f35,0xbf22be483f62bf6d,
0x3ef1bf7b3f468000,0xbdc93f55bf753ec4,0xbe95bf0e3f7fbf35,0x3f223e48bf623f6d,0xbf623e483f22bf80,0x3f7fbf0ebe953f6d,0xbf753f55bdc9bf35,0x3f46bf7b3ef13ec4,
0x3f393d49bf4a3f7b,0xbf653e793f13bf7f,0x3e603f18bf7f3f35,0xbefcbeac3f6fbf62,0x3f6abf673e893f0e,0xbf423f7dbf09be95,0x3f7cbf04bea13f6d,0xbf7e3f3e3cc9bf46,
0xbf313f80bf1dbe48,0x3ee6bf783f51bdc9,0xbf7a3f4ebd97bf35,0x3f5fbf713eb83ef1,0x3ecf3edbbf773f55,0xbf27be163f58bf75,0xbe2f3f5cbf733ec4,0xbdfbbf2c3f80bf22,
0xbe16bf223f80bf35,0x3eac3ef1bf783f55,0xbf04be953f67bf6d,0x3f2c3dc9bf4e3f7b,0x3f18bf7f3f3e0000,0xbedb3f75bf5c3e48,0x3e79bf623f71bec4,0xbd493f46bf7d3f0e,
0x3f7dbf463d493f35,0xbf713f62be79bf0e,0x3f5cbf753edb3ec4,0xbf3e3f7fbf18be48,0x3f4ebdc9bf2c3f80,0xbf673e953f04bf7b,0x3f78bef1beac3f6d,0xbf803f223e16bf55,
0xbf4a3f7dbf13be48,0x3f39bf803f273dc9,0xbf653f71becfbec4,0x3f58bf783efc3e95,0xbf773f5cbe60bf0e,0x3f6fbf673ea13ef1,0xbf7f3f3ebcc9bf35,0x3f7cbf4e3dfb3f22,
0xbf1dbe163f51bf7b,0x3f313d49bf423f7f,0xbee6beac3f6abf6d,0x3f093e79bf5f3f75,0xbe89bf043f7abf55,0x3eb83edbbf733f62,0xbd97bf2c3f80bf35,0x3e2f3f18bf7e3f46,
0xbf3500003f353f80,0x3f350000bf35bf80,0xbf3500003f353f80,0x3f350000bf35bf80,0xbf3500003f353f80,0x3f350000bf35bf80,0xbf3500003f353f80,0x3f350000bf35bf80,
0xbf35bf80bf358000,0x3f353f803f358000,0xbf35bf80bf358000,0x3f353f803f358000,0xbf35bf80bf358000,0x3f353f803f358000,0xbf35bf80bf358000,0x3f353f803f358000,
0x3f77bf783f7abf7b,0x3f6fbf713f73bf75,0x3f7fbf803f80bf80,0x3f7cbf7d3f7ebf7f,0x3f4abf4e3f51bf55,0x3f39bf3e3f42bf46,0x3f65bf673f6abf6d,0x3f58bf5c3f5fbf62,
0xbe893e79be603e48,0xbeb83eacbea13e95,0xbd973d49bcc98000,0xbe2f3e16bdfb3dc9,0xbf1d3f18bf133f0e,0xbf313f2cbf273f22,0xbee63edbbecf3ec4,0xbf093f04befc3ef1,
0xbf183f22bf2c3f35,0xbedb3ef1bf043f0e,0xbe793e95beac3ec4,0xbd493dc9be163e48,0xbf7d3f7fbf803f80,0xbf713f75bf783f7b,0xbf5c3f62bf673f6d,0xbf3e3f46bf4e3f55,
0x3f4ebf463f3ebf35,0x3f67bf623f5cbf55,0x3f78bf753f71bf6d,0x3f80bf7f3f7dbf7b,0x3e16bdc93d498000,0x3eacbe953e79be48,0x3f04bef13edbbec4,0x3f2cbf223f18bf0e,
0xbecf3eacbe893e48,0xbf273f18bf093ef1,0x3e2fbe793ea1bec4,0xbdfb3d493cc9bdc9,0x3f31bf3e3f4abf55,0x3ee6bf043f13bf22,0x3f7abf7d3f7fbf80,0x3f5fbf673f6fbf75,
0xbf6a3f71bf773f7b,0xbf423f4ebf583f62,0xbf7c3f78bf733f6d,0xbf7e3f80bf803f7f,0xbf393f2cbf1d3f0e,0xbf653f5cbf513f46,0xbe603e16bd978000,0xbefc3edbbeb83e95,
0xbf753f7bbf7f3f80,0xbf463f55bf623f6d,0xbef13f0ebf223f35,0xbdc93e48be953ec4,0x3e95be483dc90000,0x3f22bf0e3ef1bec4,0x3f62bf553f46bf35,0x3f7fbf7b3f75bf6d,
0x3e95be483dc98000,0x3f22bf0e3ef1bec4,0x3f62bf553f46bf35,0x3f7fbf7b3f75bf6d,0x3f75bf7b3f7fbf80,0x3f46bf553f62bf6d,0x3ef1bf0e3f22bf35,0x3dc9be483e95bec4,
0x3e60beac3ee6bf0e,0xbe893e16bcc9bdc9,0x3f6fbf783f7ebf80,0x3f27bf3e3f51bf62,0xbf7c3f80bf7f3f7b,0xbf4a3f5cbf6a3f75,0xbf313f18befc3ec4,0xbf733f67bf583f46,
0xbf7a3f71bf653f55,0xbf773f7dbf803f7f,0xbeb83e79bdfb8000,0xbf423f2cbf133ef1,0x3e2fbd49bd973e48,0x3f1dbf043ecfbe95,0xbf393f4ebf5f3f6d,0xbea13edbbf093f22,
0x3f71bf623f4ebf35,0x3f78bf7f3f80bf7b,0x3f2cbf463f5cbf6d,0x3e16be953edbbf0e,0xbf673f75bf7d3f80,0xbf043f22bf3e3f55,0x3d493dc9be793ec4,0x3f18bef13eacbe48,
0x3eacbef13f18bf35,0xbe793dc93d49be48,0xbf3e3f22bf043ec4,0xbf7d3f75bf673f55,0x3edbbe953e168000,0x3f5cbf463f2cbf0e,0x3f80bf7f3f78bf6d,0x3f4ebf623f71bf7b,
0xbd973e79becf3f0e,0x3f13bedb3e89bdc9,0xbf7e3f80bf7a3f6d,0xbf313f4ebf653f75,0xbea13e163cc9be48,0xbf583f3ebf1d3ef1,0x3f5fbf713f7cbf80,0x3eb8bf043f27bf46,
0x3f7fbf783f6abf55,0x3f51bf673f77bf7f,0x3dfb3d49be603ec4,0x3f39bf183ee6be95,0xbf733f7dbf803f7b,0xbf093f2cbf4a3f62,0xbefc3eacbe2f8000,0xbf6f3f5cbf423f22,
0xbf553f6dbf7b3f80,0xbe483ec4bf0e3f35,0x3f0ebec43e480000,0x3f7bbf6d3f55bf35,0x3f55bf6d3f7bbf80,0x3e48bec43f0ebf35,0xbf0e3ec4be480000,0xbf7b3f6dbf553f35,
0x3f0ebec43e488000,0x3f7bbf6d3f55bf35,0x3f55bf6d3f7bbf80,0x3e48bec43f0ebf35,0xbf0e3ec4be488000,0xbf7b3f6dbf553f35,0xbf553f6dbf7b3f80,0xbe483ec4bf0e3f35,
0xbf423f18becf3e48,0xbf7c3f80bf773f62,0x3f4abf673f7abf80,0x3cc9be793ee6bf22,0x3f73bf5c3f39bf0e,0x3f58bf713f7ebf7f,0xbefc3f2cbf513f6d,0x3eb8be16bd973e95,
0xbf273f4ebf6a3f7b,0x3e2f3d49be893ef1,0xbf1d3edbbe608000,0xbf803f78bf653f46,0x3ea1bf043f31bf55,0xbf093eacbdfbbdc9,0x3f5fbf3e3f13bec4,0x3f6fbf7d3f7fbf75,
0x3d49be953f04bf35,0xbf4e3f22bedb3e48,0xbf713f7fbf7d3f6d,0xbe793ef1bf2c3f55,0xbf3e3f62bf783f80,0x3e163dc9beac3f0e,0x3f67bf463f18bec4,0x3f5cbf753f80bf7b,
0xbf803f75bf5c3f35,0xbf183f46bf673f7b,0x3eacbdc9be163ec4,0x3f78bf623f3ebf0e,0x3f2cbef13e798000,0x3f7dbf7f3f71bf55,0x3edbbf223f4ebf6d,0xbf043e95bd49be48,
0x3f09bf3e3f65bf7b,0xbefc3e793cc9be95,0x3ecfbe16bdfb3ec4,0x3f7fbf713f51bf22,0xbf7c3f67bf423f0e,0xbf1d3f4ebf6f3f7f,0x3f31bf5c3f77bf80,0xbea13d493e60bef1,
0xbf583f2cbee63e48,0xbf5f3f78bf803f75,0x3f6abf7d3f7ebf6d,0x3d97beac3f13bf46,0xbe2f3edbbf273f55,0x3f4abf183eb8bdc9,0xbf393f04be898000,0xbf733f80bf7a3f62,
0xbf223f55bf753f80,0x3ef1be48bdc93ec4,0x3f7fbf7b3f62bf35,0x3e95bf0e3f46bf6d,0xbf463f0ebe950000,0xbf623f7bbf7f3f6d,0x3dc93e48bef13f35,0x3f75bf553f22bec4,
0x3f46bf0e3e958000,0x3f62bf7b3f7fbf6d,0xbdc9be483ef1bf35,0xbf753f55bf223ec4,0xbf223f55bf753f80,0x3ef1be48bdc93ec4,0x3f7fbf7b3f62bf35,0x3e95bf0e3f46bf6d,
0xbf6f3f80bf773f55,0x3d973e79bf093f46,0x3f13bf4e3f73bf80,0xbf1d3eacbcc9be95,0xbf313edbbdfbbe48,0xbf653f7dbf7c3f62,0x3f7abf5c3f27bec4,0x3efcbf3e3f6abf7f,
0x3eb8bd49be893f0e,0x3f7fbf783f58bf22,0xbf513f18bea18000,0xbf4a3f71bf803f75,0xbf393f67bf7e3f7b,0x3ee6be16be2f3ef1,0x3e60bf043f42bf6d,0xbf5f3f2cbecf3dc9,
0xbf783f7fbf673f35,0x3d493e95bf183f55,0x3f7dbf623f2cbec4,0x3eacbf223f5cbf7b,0xbf043f46bf713f80,0x3f3ebef13e163e48,0x3f4ebf753f80bf6d,0xbedb3dc93e79bf0e,
0x3e793dc9bedb3f35,0x3f80bf753f4ebf0e,0x3e16bef13f3ebf6d,0xbf713f46bf043e48,0x3f5cbf223eac8000,0x3f2cbf623f7dbf7b,0xbf183e953d49bec4,0xbf673f7fbf783f55,
0xbf5f3f7dbf7a3f55,0x3ecfbd49bea13f22,0x3f42bf713f80bf6d,0xbf133e793dfbbef1,0xbf1d3f5cbf7c3f7b,0x3f39bedb3d973e95,0x3ee6bf3e3f6fbf80,0xbf583f18be89bdc9,
0x3efcbe16be603f0e,0x3f6abf803f73bf46,0xbf273eac3cc9bec4,0xbf513f78bf7e3f62,0x3f4abf043e2f3e48,0x3f31bf673f7fbf75,0xbf653f2cbeb88000,0xbf093f4ebf773f7f,
0xbec43f35bf6d3f80,0x3f6dbf353ec40000,0x3ec4bf353f6dbf80,0xbf6d3f35bec40000,0xbec43f35bf6d3f80,0x3f6dbf353ec40000,0x3ec4bf353f6dbf80,0xbf6d3f35bec40000,
0x3f6dbf353ec48000,0x3ec4bf353f6dbf80,0xbf6d3f35bec48000,0xbec43f35bf6d3f80,0x3f6dbf353ec48000,0x3ec4bf353f6dbf80,0xbf6d3f35bec48000,0xbec43f35bf6d3f80,
0xbdfb3f04bf513f7b,0x3f80bf673f27be95,0x3ea1bf2c3f6abf80,0xbf7a3f4ebefc3dc9,0x3e893e16bf093f55,0x3f6fbf803f65bf22,0xbd97beac3f31bf6d,0xbf7c3f78bf4a3ef1,
0x3f7ebf5c3f13be48,0x3cc9bedb3f42bf75,0xbf733f3ebecf8000,0xbe603f18bf5f3f7f,0x3f77bf7d3f58bf0e,0xbeb8bd493ee6bf46,0xbf7f3f71bf393ec4,0x3e2f3e79bf1d3f62,
0x3f04bdc9beac3f35,0x3f3ebf753f7dbf55,0xbf4e3ef1bd49bec4,0xbedb3f46bf783f7b,0xbe793f22bf673f80,0x3f80bf623f18be48,0xbe16be953f2cbf6d,0xbf713f7fbf5c3f0e,
0x3f5cbf7f3f71bf35,0xbf2c3e953e16bf0e,0xbf183f62bf803f6d,0x3f67bf223e793e48,0x3f78bf463edb8000,0x3d49bef13f4ebf7b,0xbf7d3f75bf3e3ec4,0x3eac3dc9bf043f55,
0x3f80bf673f1dbe48,0xbea1be163f13bf62,0xbf583f04bd97bec4,0xbe893f2cbf6f3f7f,0x3ecf3d49befc3f55,0x3f42bf783f7abf46,0x3e2fbf183f65bf80,0xbf7e3f71bf313e95,
0xbcc9bedb3f4abf7b,0xbf733f7dbf513ef1,0xbf093f5cbf7f3f6d,0x3f77bf3e3eb83dc9,0x3f6abf803f5fbf0e,0xbf273e793e60bf22,0xbf7c3f4ebee68000,0x3dfb3eacbf393f75,
0xbdc93f0ebf623f80,0x3f75bf7b3f46bec4,0xbf223e483e95bf35,0xbef13f55bf7f3f6d,0x3f7fbf553ef10000,0xbe95be483f22bf6d,0xbf463f7bbf753f35,0x3f62bf0e3dc93ec4,
0x3f7fbf553ef18000,0xbe95be483f22bf6d,0xbf463f7bbf753f35,0x3f62bf0e3dc93ec4,0x3dc9bf0e3f62bf80,0xbf753f7bbf463ec4,0x3f22be48be953f35,0x3ef1bf553f7fbf6d,
0x3f51bedbbd973f0e,0x3dfbbf183f6abf7f,0x3cc9bf043f5fbf80,0xbf653f80bf583ef1,0x3e60bf2c3f73bf7b,0xbf773f78bf393e95,0xbf6f3f7dbf4a3ec4,0x3f42beacbe2f3f22,
0x3f13bf673f7fbf55,0xbf7e3f4ebecfbdc9,0xbf803f5cbefc8000,0x3ee63d49bf093f62,0xbf7a3f3ebea1be48,0x3e893e79bf313f75,0x3eb83e16bf1d3f6d,0x3f27bf713f7cbf46,
0x3f2cbf753f78bf35,0xbf7d3f46beacbe48,0x3edb3dc9bf183f6d,0x3f04bf623f80bf55,0x3d493ef1bf5c3f80,0x3f4ebf7f3f67bf0e,0xbf713f22be16bec4,0x3e793e95bf3e3f7b,
0xbf3e3e953e79bf35,0xbe163f22bf713f7b,0x3f67bf7f3f4ebec4,0xbf5c3ef13d49bf0e,0x3f80bf623f048000,0xbf183dc93edbbf55,0xbeac3f46bf7d3f6d,0x3f78bf753f2cbe48,
0xbf653f043cc9bf0e,0x3e603eacbf4a3f7f,0xbe893f3ebf7c3f6d,0x3f6abf7d3f42be95,0x3f7fbf4e3eb83e48,0xbf133d493efcbf62,0xbdfbbedb3f58bf80,0xbf313f78bf733f22,
0xbee63f5cbf803f55,0x3f7abf713f1dbdc9,0x3f77bf2c3e2f3ec4,0xbecfbe163f27bf75,0x3d97bf183f6fbf7b,0xbf513f80bf5f3ef1,0xbf7e3f67bf098000,0x3f39be79bea13f46,
0x3e483ec4bf553f80,0x3f0ebf6d3f7bbf35,0xbf7b3f6dbf0e0000,0x3f55bec4be483f35,0xbe48bec43f55bf80,0xbf0e3f6dbf7b3f35,0x3f7bbf6d3f0e0000,0xbf553ec43e48bf35,
0x3f7bbf6d3f0e8000,0xbf553ec43e48bf35,0x3e483ec4bf553f80,0x3f0ebf6d3f7bbf35,0xbf7b3f6dbf0e8000,0x3f55bec4be483f35,0xbe48bec43f55bf80,0xbf0e3f6dbf7b3f35,
0x3f65bf7d3f39be48,0xbf7a3f2cbdfbbef1,0xbe89beac3f51bf80,0xbecf3f5cbf7f3f46,0xbf273f78bf6f3f0e,0x3f7cbf673efc3dc9,0x3f1dbd49bf093f6d,0x3cc9bf183f73bf75,
0xbee6be163f31bf7b,0xbe603f3ebf7e3f62,0xbf773f71bf138000,0x3f6abf04bd973f22,0x3f42be79beb83f55,0xbe2fbedb3f5fbf7f,0x3f4abf803f58bec4,0xbf803f4ebea1be95,
0xbf673ef13e16bf35,0x3f043dc9bf2c3f7b,0x3d49bf223f78bf6d,0xbf183f75bf713f0e,0x3eac3e95bf4e3f80,0x3e79bf463f80bf55,0xbf3e3f7fbf5c3ec4,0x3f7dbf623edb3e48,
0xbedb3f62bf7d3f35,0x3f5cbf7f3f3ebe48,0xbf803f46be79bec4,0x3f4ebe95beac3f55,0x3f71bf753f188000,0xbf783f22bd49bf0e,0x3f2cbdc9bf043f6d,0xbe16bef13f67bf7b,
0x3f133d49bf273f7b,0xbdfbbf043f6fbf75,0x3f80bf4e3e893ec4,0xbf653edb3e60bf46,0x3f09bf713f73bf0e,0xbf5f3f7dbf313dc9,0xbecfbe793f4abf80,0xbd973f2cbf7c3f62,
0x3f51bf803f42be48,0xbf7e3f5cbeb8be95,0xbcc9bf183f77bf6d,0xbee63f67bf7a3f22,0xbf583eac3ea1bf55,0x3efc3e16bf393f7f,0xbf6a3f78bf1d8000,0x3f7fbf3e3e2f3ef1,
0x3ef13e48bf463f80,0xbdc9bf0e3f75bf6d,0xbe953f55bf7f3f35,0x3f22bf7b3f62bec4,0xbf623f7bbf220000,0x3f7fbf553e953ec4,0xbf753f0e3dc9bf35,0x3f46be48bef13f6d,
0x3f62bf7b3f228000,0xbf7f3f55be95bec4,0x3f75bf0ebdc93f35,0xbf463e483ef1bf6d,0x3ef13e48bf463f80,0xbdc9bf0e3f75bf6d,0xbe953f55bf7f3f35,0x3f22bf7b3f62bec4,
0x3cc9bf2c3f7ebf55,0xbea13f5cbf7c3f22,0xbf09be163f42bf80,0x3e893edbbf6a3f75,0x3f6fbf713efc3e48,0xbf7f3f4ebe60bef1,0x3f13bf783f65bec4,0xbf4a3f80bf393dc9,
0xbf803f3ebdfbbf0e,0x3f73bf04be2f3f46,0xbf583f7dbf278000,0x3f77bf673ecf3e95,0xbeb8beac3f5fbf7b,0x3d973f18bf7a3f62,0xbf513e793ee6bf6d,0x3f1d3d49bf313f7f,
0xbe163f46bf803f35,0x3eacbf623f78bf0e,0xbf043f75bf673ec4,0x3f2cbf7f3f4ebe48,0x3f183dc9bf3e3f80,0xbedbbe953f5cbf7b,0x3e793ef1bf713f6d,0xbd49bf223f7dbf55,
0x3f7dbf22bd493f35,0xbf713ef13e79bf55,0x3f5cbe95bedb3f6d,0xbf3e3dc93f18bf7b,0x3f4ebf7f3f2c8000,0xbf673f75bf04be48,0x3f78bf623eac3ec4,0xbf803f46be16bf0e,
0xbdfbbf183f7cbf55,0x3cc93f2cbf7f3f46,0xbea1bedb3f6fbf6d,0x3e603f04bf773f62,0xbefcbe793f58bf7b,0x3ecf3eacbf653f75,0xbf27bd493f39bf80,0x3f133e16bf4a3f7f,
0xbf7e3f4ebe2fbf0e,0x3f80bf3e3d973f22,0xbf733f67beb8bec4,0x3f7abf5c3e893ef1,0xbf5f3f78bf09be48,0x3f6abf713ee63e95,0xbf423f80bf318000,0x3f51bf7d3f1d3dc9,
0xbf3500003f353f80,0x3f350000bf35bf80,0xbf3500003f353f80,0x3f350000bf35bf80,0xbf3500003f353f80,0x3f350000bf35bf80,0xbf3500003f353f80,0x3f350000bf35bf80,
0xbf35bf80bf358000,0x3f353f803f358000,0xbf35bf80bf358000,0x3f353f803f358000,0xbf35bf80bf358000,0x3f353f803f358000,0xbf35bf80bf358000,0x3f353f803f358000,
0x3efcbf043f09bf0e,0x3ecfbedb3ee6bef1,0x3f27bf2c3f31bf35,0x3f13bf183f1dbf22,0x3dfbbe163e2fbe48,0x3cc9bd493d97bdc9,0x3ea1beac3eb8bec4,0x3e60be793e89be95,
0xbf5f3f5cbf583f55,0xbf6a3f67bf653f62,0xbf423f3ebf393f35,0xbf513f4ebf4a3f46,0xbf7e3f7dbf7c3f7b,0xbf803f80bf7f3f7f,0xbf733f71bf6f3f6d,0xbf7a3f78bf773f75,
0x3f4ebf463f3ebf35,0x3f67bf623f5cbf55,0x3f78bf753f71bf6d,0x3f80bf7f3f7dbf7b,0x3e16bdc93d490000,0x3eacbe953e79be48,0x3f04bef13edbbec4,0x3f2cbf223f18bf0e,
0x3f18bf223f2cbf35,0x3edbbef13f04bf0e,0x3e79be953eacbec4,0x3d49bdc93e16be48,0x3f7dbf7f3f80bf80,0x3f71bf753f78bf7b,0x3f5cbf623f67bf6d,0x3f3ebf463f4ebf55,
0xbeb83edbbefc3f0e,0xbd973e16be603e95,0xbf513f5cbf653f6d,0xbf1d3f2cbf393f46,0xbf803f80bf7e3f7b,0xbf733f78bf7c3f7f,0xbf583f4ebf423f35,0xbf773f71bf6a3f62,
0x3f6fbf673f5fbf55,0x3f7fbf7d3f7abf75,0x3f13bf043ee6bec4,0x3f4abf3e3f31bf22,0x3cc93d49bdfb3e48,0x3ea1be793e2fbdc9,0xbf093f18bf273f35,0xbe893eacbecf3ef1,
0x3f75bf7b3f7fbf80,0x3f46bf553f62bf6d,0x3ef1bf0e3f22bf35,0x3dc9be483e95bec4,0xbe953e48bdc90000,0xbf223f0ebef13ec4,0xbf623f55bf463f35,0xbf7f3f7bbf753f6d,
0xbe953e48bdc98000,0xbf223f0ebef13ec4,0xbf623f55bf463f35,0xbf7f3f7bbf753f6d,0xbf753f7bbf7f3f80,0xbf463f55bf623f6d,0xbef13f0ebf223f35,0xbdc93e48be953ec4,
0x3f09bedb3ea1be48,0x3f5fbf4e3f39bf22,0xbecf3f04bf1d3f35,0x3d973d49be2f3e95,0x3f13bf2c3f42bf55,0x3dfbbe793eb8bef1,0x3f80bf7d3f77bf6d,0x3f65bf713f7abf7f,
0x3f58bf673f73bf7b,0x3efcbf183f31bf46,0x3f6abf5c3f4abf35,0x3f7fbf803f7cbf75,0xbf513f3ebf273f0e,0xbf7e3f78bf6f3f62,0x3cc9be163e89bec4,0xbee63eacbe603dc9,
0xbeac3ef1bf183f35,0x3e79bdc9bd493e48,0x3f3ebf223f04bec4,0x3f7dbf753f67bf55,0xbedb3e95be160000,0xbf5c3f46bf2c3f0e,0xbf803f7fbf783f6d,0xbf4e3f62bf713f7b,
0x3f71bf623f4ebf35,0x3f78bf7f3f80bf7b,0x3f2cbf463f5cbf6d,0x3e16be953edbbf0e,0xbf673f75bf7d3f80,0xbf043f22bf3e3f55,0x3d493dc9be793ec4,0x3f18bef13eacbe48,
0xbf423f5cbf6f3f7b,0xbe2f3eacbefc3f22,0xbf4a3f2cbf093ec4,0xbf803f7dbf733f62,0x3ee6bf183f39bf55,0xbe603d493dfbbe95,0x3f77bf673f51bf35,0x3f6abf783f7fbf7f,
0x3f27bf043eb8be48,0x3f7cbf713f5fbf46,0xbf1d3f3ebf583f6d,0x3cc93e16bea13ef1,0xbf653f4ebf313f0e,0xbf7a3f80bf7e3f75,0x3e89bedb3f13bf35,0xbecf3e79bd97bdc9,
0xbf553f6dbf7b3f80,0xbe483ec4bf0e3f35,0x3f0ebec43e480000,0x3f7bbf6d3f55bf35,0x3f55bf6d3f7bbf80,0x3e48bec43f0ebf35,0xbf0e3ec4be480000,0xbf7b3f6dbf553f35,
0x3f0ebec43e488000,0x3f7bbf6d3f55bf35,0x3f55bf6d3f7bbf80,0x3e48bec43f0ebf35,0xbf0e3ec4be488000,0xbf7b3f6dbf553f35,0xbf553f6dbf7b3f80,0xbe483ec4bf0e3f35,
0xbf7f3f7dbf6f3f55,0xbf133f3ebf5f3f75,0x3dfbbeac3f09bf35,0xbf313f04bea13dc9,0x3f65bf783f80bf7b,0x3e60bedb3f1dbf46,0x3e89bd49be2f3ec4,0x3f6abf4e3f27bef1,
0x3d973e16beb83f0e,0x3f51bf2c3efcbe95,0xbf7e3f71bf583f35,0xbf393f5cbf733f7f,0xbee63e79bcc9be48,0xbf7a3f67bf4a3f22,0x3f77bf803f7cbf6d,0x3ecfbf183f42bf62,
0xbf803f75bf5c3f35,0xbf183f46bf673f7b,0x3eacbdc9be163ec4,0x3f78bf623f3ebf0e,0x3f2cbef13e790000,0x3f7dbf7f3f71bf55,0x3edbbf223f4ebf6d,0xbf043e95bd49be48,
0xbd493e95bf043f35,0x3f4ebf223edbbe48,0x3f71bf7f3f7dbf6d,0x3e79bef13f2cbf55,0x3f3ebf623f78bf80,0xbe16bdc93eacbf0e,0xbf673f46bf183ec4,0xbf5c3f75bf803f7b,
0xbf7a3f80bf733f55,0xbe893f04bf393f62,0x3eb8bf183f4abf6d,0xbf273edbbe2fbdc9,0x3f13beac3d973e48,0x3f7ebf7d3f6abf46,0xbf803f78bf5f3f35,0xbee63f2cbf583f75,
0x3e603d49bea13f0e,0x3f77bf5c3f31bef1,0xbf6f3f4ebf1d3ec4,0xbf423f67bf7c3f7f,0x3f51bf713f7fbf7b,0xbdfbbe163ecfbf22,0x3cc93e79befc3f35,0x3f65bf3e3f09be95,
0x3f22bf553f75bf80,0xbef13e483dc9bec4,0xbf7f3f7bbf623f35,0xbe953f0ebf463f6d,0x3f46bf0e3e950000,0x3f62bf7b3f7fbf6d,0xbdc9be483ef1bf35,0xbf753f55bf223ec4,
0xbf463f0ebe958000,0xbf623f7bbf7f3f6d,0x3dc93e48bef13f35,0x3f75bf553f22bec4,0x3f22bf553f75bf80,0xbef13e483dc9bec4,0xbf7f3f7bbf623f35,0xbe953f0ebf463f6d,
0x3ecfbf2c3f5fbf7b,0xbf423f04be60bdc9,0x3e2f3e16bee63f35,0x3f7ebf673f39bef1,0x3f80bf713f4abf0e,0x3ea1bf183f51bf75,0xbf583f78bf7f3f6d,0x3e893d49beb83f22,
0xbf6a3f3ebefc3e48,0xbf273f5cbf7a3f7f,0x3f7cbf7d3f65bf35,0x3dfbbedb3f31bf62,0x3cc9beac3f1dbf55,0xbf733f4ebf133e95,0x3f09be79bd973ec4,0x3f77bf803f6fbf46,
0xbe79bdc93edbbf35,0xbf803f75bf4e3f0e,0xbe163ef1bf3e3f6d,0x3f71bf463f04be48,0xbf5c3f22beac0000,0xbf2c3f62bf7d3f7b,0x3f18be95bd493ec4,0x3f67bf7f3f78bf55,
0xbf783f7fbf673f35,0x3d493e95bf183f55,0x3f7dbf623f2cbec4,0x3eacbf223f5cbf7b,0xbf043f46bf713f80,0x3f3ebef13e163e48,0x3f4ebf753f80bf6d,0xbedb3dc93e79bf0e,
0xbf773f4ebf093e48,0xbeb83f2cbf653f7f,0x3f7fbf673f31bec4,0x3e2fbf043f4abf75,0xbf7e3f78bf513f0e,0x3cc93eacbf273f62,0x3f73bf803f6abf35,0xbe60be163efcbf46,
0xbe893f18bf583f7b,0x3f6fbf3e3ee6bdc9,0x3d97bedb3f39bf6d,0xbf7c3f5cbf1d3e95,0x3dfb3e79bf133f55,0x3f80bf713f42bef1,0xbea1bd493ecfbf35,0xbf7a3f7dbf5f3f22,
0xbec43f35bf6d3f80,0x3f6dbf353ec40000,0x3ec4bf353f6dbf80,0xbf6d3f35bec40000,0xbec43f35bf6d3f80,0x3f6dbf353ec40000,0x3ec4bf353f6dbf80,0xbf6d3f35bec40000,
0x3f6dbf353ec48000,0x3ec4bf353f6dbf80,0xbf6d3f35bec48000,0xbec43f35bf6d3f80,0x3f6dbf353ec48000,0x3ec4bf353f6dbf80,0xbf6d3f35bec48000,0xbec43f35bf6d3f80,
0x3f1dbe79be2f3f0e,0x3f39bf713f7fbf62,0xbee63d493eb8bf35,0xbf583f7dbf773f46,0x3f5fbf183e603e48,0x3ecfbf3e3f73bf7f,0xbf423edbbcc9bec4,0xbf133f5cbf7e3f75,
0x3f4abf783f7cbf55,0xbf313eac3d97bef1,0xbf653f80bf6f3f35,0x3f09be16be893f22,0x3efcbf4e3f7abf7b,0xbf6a3f2cbea1bdc9,0xbf273f67bf803f6d,0x3f51bf043dfb3e95,
0x3f5cbf7f3f71bf35,0xbf2c3e953e16bf0e,0xbf183f62bf803f6d,0x3f67bf223e793e48,0x3f78bf463edb0000,0x3d49bef13f4ebf7b,0xbf7d3f75bf3e3ec4,0x3eac3dc9bf043f55,
0xbf043dc93eacbf35,0xbf3e3f75bf7d3f55,0x3f4ebef13d493ec4,0x3edbbf463f78bf7b,0x3e79bf223f67bf80,0xbf803f62bf183e48,0x3e163e95bf2c3f6d,0x3f71bf7f3f5cbf0e,
0xbf393eac3dfbbf0e,0xbee63f4ebf7c3f75,0x3e603e79bf273f6d,0x3f5fbf803f6abf22,0x3eb8bf3e3f77bf7b,0xbf7f3f5cbf093dc9,0xbf513f7dbf733f35,0x3f4abedbbcc93ef1,
0xbf313f71bf7e3f55,0x3f65bf183e2f3e95,0x3f7abf783f42bec4,0xbefc3d493ecfbf46,0xbf6f3f2cbe89be48,0xbd973f04bf583f7f,0x3f13be16bea13f35,0x3f1dbf673f80bf62,
0x3dc9bf0e3f62bf80,0xbf753f7bbf463ec4,0x3f22be48be953f35,0x3ef1bf553f7fbf6d,0xbf7f3f55bef10000,0x3e953e48bf223f6d,0x3f46bf7b3f75bf35,0xbf623f0ebdc9bec4,
0xbf7f3f55bef18000,0x3e953e48bf223f6d,0x3f46bf7b3f75bf35,0xbf623f0ebdc9bec4,0xbdc93f0ebf623f80,0x3f75bf7b3f46bec4,0xbf223e483e95bf35,0xbef13f55bf7f3f6d,
0xbf7c3f71bf273e48,0x3f1dbe16beb83f46,0x3f31be79be893f35,0x3ea1bf3e3f7abf75,0x3f09bd49bee63f55,0x3efcbf5c3f80bf62,0x3ecfbf4e3f7ebf6d,0xbf7f3f67bf133dc9,
0x3e2f3eacbf423f7b,0x3f4abf7d3f6fbf22,0x3f39bf783f77bf35,0xbf733f2cbe60be95,0x3f58bf803f65bf0e,0xbf5f3f04bcc9bef1,0xbf6a3f18bdfbbec4,0x3d973edbbf513f7f,
0x3f3ebe95be793f35,0x3e16bf223f71bf7b,0xbf673f7fbf4e3ec4,0x3f5cbef1bd493f0e,0xbf803f62bf040000,0x3f18bdc9bedb3f55,0x3eacbf463f7dbf6d,0xbf783f75bf2c3e48,
0x3f2cbf753f78bf35,0xbf7d3f46beacbe48,0x3edb3dc9bf183f6d,0x3f04bf623f80bf55,0x3d493ef1bf5c3f80,0x3f4ebf7f3f67bf0e,0xbf713f22be16bec4,0x3e793e95bf3e3f7b,
0xbea1be793f39bf7b,0xbf093f67bf7e3f46,0xbf5f3f80bf513ec4,0x3f6fbf183d973ef1,0x3f27be16becf3f55,0x3e2fbf2c3f77bf75,0x3f1dbf713f7abf35,0xbf803f5cbee6bdc9,
0xbf733f78bf313e48,0x3f58bedbbdfb3f22,0x3efc3d49bf133f6d,0x3eb8bf4e3f7fbf62,0x3f42bf7d3f6abf0e,0xbf7c3f3ebe89be95,0xbf4a3eac3e60bf35,0x3cc93f04bf653f7f,
0x3e483ec4bf553f80,0x3f0ebf6d3f7bbf35,0xbf7b3f6dbf0e0000,0x3f55bec4be483f35,0xbe48bec43f55bf80,0xbf0e3f6dbf7b3f35,0x3f7bbf6d3f0e0000,0xbf553ec43e48bf35,
0x3f7bbf6d3f0e8000,0xbf553ec43e48bf35,0x3e483ec4bf553f80,0x3f0ebf6d3f7bbf35,0xbf7b3f6dbf0e8000,0x3f55bec4be483f35,0xbe48bec43f55bf80,0xbf0e3f6dbf7b3f35,
0x3ea1bf4e3f80bf55,0xbf583f80bf4a3e95,0xbf5f3edb3e2fbf35,0x3eb83e79bf423f7f,0x3d973f04bf6a3f7b,0x3f13bf713f77bf22,0x3f7ebf3e3e603ec4,0xbf313e163ee6bf62,
0xbf733f18bcc9bf0e,0x3f093d49bf1d3f75,0xbefc3f67bf7c3f35,0x3f6fbf783f27bdc9,0x3f7fbf5c3ecf3e48,0xbf513eac3e89bf46,0x3dfbbf2c3f7abf6d,0xbf393f7dbf653ef1,
0xbedb3f62bf7d3f35,0x3f5cbf7f3f3ebe48,0xbf803f46be79bec4,0x3f4ebe95beac3f55,0x3f71bf753f180000,0xbf783f22bd49bf0e,0x3f2cbdc9bf043f6d,0xbe16bef13f67bf7b,
0x3f67bef1be163f35,0xbf04bdc93f2cbf7b,0xbd493f22bf783f6d,0x3f18bf753f71bf0e,0xbeacbe953f4ebf80,0xbe793f46bf803f55,0x3f3ebf7f3f5cbec4,0xbf7d3f62bedbbe48,
0x3e2fbf3e3f7fbf55,0xbf1d3f78bf6a3ef1,0xbf393e163efcbf6d,0x3ea13eacbf583f7f,0xbf7a3f67bee6be48,0x3f77bf18bcc93f22,0xbeb83f5cbf7e3f35,0x3f42bf803f51be95,
0xbf7c3f2cbd97bf0e,0x3f4abe79becf3f62,0xbf313f7dbf5f3ec4,0x3f73bf713f093dc9,0x3e603edbbf653f7b,0x3e89bf4e3f80bf46,0x3f6fbf04bdfb3f35,0xbf273d493f13bf75,
0xbef1be483f46bf80,0x3dc93f0ebf753f6d,0x3e95bf553f7fbf35,0xbf223f7bbf623ec4,0x3f62bf7b3f220000,0xbf7f3f55be95bec4,0x3f75bf0ebdc93f35,0xbf463e483ef1bf6d,
0xbf623f7bbf228000,0x3f7fbf553e953ec4,0xbf753f0e3dc9bf35,0x3f46be48bef13f6d,0xbef1be483f46bf80,0x3dc93f0ebf753f6d,0x3e95bf553f7fbf35,0xbf223f7bbf623ec4,
0x3f31bd49bf1d3f7b,0xbee6be793f51bf7f,0x3f7abf18bd973f35,0xbf5f3eac3eb8bf62,0xbecf3f67bf773f0e,0x3f27bf7d3f58be95,0x3e2f3f04bf733f6d,0x3dfbbf3e3f80bf46,
0x3f39bf803f4abe48,0xbf653f78bf13bdc9,0x3e60bf4e3f7fbf35,0xbefc3f71bf6f3ef1,0x3f6abedbbe893f55,0xbf423e163f09bf75,0x3f7cbf5c3ea13ec4,0xbf7e3f2cbcc9bf22,
0xbf7d3f223d49bf35,0x3f71bef1be793f55,0xbf5c3e953edbbf6d,0x3f3ebdc9bf183f7b,0xbf4e3f7fbf2c0000,0x3f67bf753f043e48,0xbf783f62beacbec4,0x3f80bf463e163f0e,
0xbe163f46bf803f35,0x3eacbf623f78bf0e,0xbf043f75bf673ec4,0x3f2cbf7f3f4ebe48,0x3f183dc9bf3e3f80,0xbedbbe953f5cbf7b,0x3e793ef1bf713f6d,0xbd49bf223f7dbf55,
0x3f1dbf7d3f51be48,0xbf313f80bf423dc9,0x3ee6bf713f6abec4,0xbf093f78bf5f3e95,0x3e89bf5c3f7abf0e,0xbeb83f67bf733ef1,0x3d97bf3e3f80bf35,0xbe2f3f4ebf7e3f22,
0xbf4a3e163f13bf7b,0x3f39bd49bf273f7f,0xbf653eac3ecfbf6d,0x3f58be79befc3f75,0xbf773f043e60bf55,0x3f6fbedbbea13f62,0xbf7f3f2c3cc9bf35,0x3f7cbf18bdfb3f46,
0x3f350000bf353f80,0xbf3500003f35bf80,0x3f350000bf353f80,0xbf3500003f35bf80,0x3f350000bf353f80,0xbf3500003f35bf80,0x3f350000bf353f80,0xbf3500003f35bf80,
0xbf353f80bf358000,0x3f35bf803f358000,0xbf353f80bf358000,0x3f35bf803f358000,0xbf353f80bf358000,0x3f35bf803f358000,0xbf353f80bf358000,0x3f35bf803f358000,
0x3e893f78be60bf7b,0x3eb83f71bea1bf75,0x3d973f80bcc9bf80,0x3e2f3f7dbdfbbf7f,0x3f1d3f4ebf13bf55,0x3f313f3ebf27bf46,0x3ee63f67becfbf6d,0x3f093f5cbefcbf62,
0x3f77be79bf7a3e48,0x3f6fbeacbf733e95,0x3f7fbd49bf808000,0x3f7cbe16bf7e3dc9,0x3f4abf18bf513f0e,0x3f39bf2cbf423f22,0x3f65bedbbf6a3ec4,0x3f58bf04bf5f3ef1,
0xbf4ebf223f3e3f35,0xbf67bef13f5c3f0e,0xbf78be953f713ec4,0xbf80bdc93f7d3e48,0xbe16bf7f3d493f80,0xbeacbf753e793f7b,0xbf04bf623edb3f6d,0xbf2cbf463f183f55,
0xbf183f463f2cbf35,0xbedb3f623f04bf55,0xbe793f753eacbf6d,0xbd493f7f3e16bf7b,0xbf7d3dc93f808000,0xbf713e953f78be48,0xbf5c3ef13f67bec4,0xbf3e3f223f4ebf0e,
0x3f6abeacbf773e48,0x3f42bf18bf583ef1,0x3f7c3e79bf73bec4,0x3f7ebd49bf80bdc9,0x3f393f3ebf1dbf55,0x3f653f04bf51bf22,0x3e603f7dbd97bf80,0x3efc3f67beb8bf75,
0xbecfbf713e893f7b,0xbf27bf4e3f093f62,0x3e2fbf78bea13f6d,0xbdfbbf80bcc93f7f,0x3f31bf2cbf4a3f0e,0x3ee6bf5cbf133f46,0x3f7abe16bf7f8000,0x3f5fbedbbf6f3e95,
0xbe95bf7b3dc93f80,0xbf22bf553ef13f6d,0xbf62bf0e3f463f35,0xbf7fbe483f753ec4,0xbf753e483f7f0000,0xbf463f0e3f62bec4,0xbef13f553f22bf35,0xbdc93f7b3e95bf6d,
0xbf753e483f7f8000,0xbf463f0e3f62bec4,0xbef13f553f22bf35,0xbdc93f7b3e95bf6d,0x3e953f7bbdc9bf80,0x3f223f55bef1bf6d,0x3f623f0ebf46bf35,0x3f7f3e48bf75bec4,
0x3f7a3eacbf65bf0e,0x3f77be16bf80bdc9,0x3eb83f78bdfbbf80,0x3f423f3ebf13bf62,0xbe2fbf80bd973f7b,0xbf1dbf5c3ecf3f75,0x3f39bf18bf5f3ec4,0x3ea1bf67bf093f46,
0x3e60bf71bee63f55,0xbe89bf7d3cc93f7f,0x3f6fbe79bf7e8000,0x3f27bf2cbf513ef1,0xbf7c3d493f7f3e48,0xbf4a3f043f6abe95,0xbf31bf4e3efc3f6d,0xbf73bedb3f583f22,
0xbeac3f623f18bf35,0x3e793f7f3d49bf7b,0x3f3e3f46bf04bf6d,0x3f7d3e95bf67bf0e,0xbedbbf753e163f80,0xbf5cbf223f2c3f55,0xbf80bdc93f783ec4,0xbf4e3ef13f71be48,
0x3f713ef1bf4ebf35,0x3f78bdc9bf80be48,0x3f2cbf22bf5c3ec4,0x3e16bf75bedb3f55,0xbf673e953f7d8000,0xbf043f463f3ebf0e,0x3d493f7f3e79bf6d,0x3f183f62beacbf7b,
0xbf7fbe793f6a3f0e,0xbf513edb3f77bdc9,0xbdfbbf80be603f6d,0xbf39bf4e3ee63f75,0x3f73be16bf80be48,0x3f09bf3ebf4a3ef1,0x3efc3f71be2fbf80,0x3f6f3f04bf42bf46,
0xbd973f783ecfbf55,0x3f133f67be89bf7f,0xbf7ebd493f7a3ec4,0xbf313f183f65be95,0xbea1bf7dbcc93f7b,0xbf58bf2c3f1d3f62,0x3f5fbeacbf7c8000,0x3eb8bf5cbf273f22,
0xbf0ebf6d3e483f80,0xbf7bbec43f553f35,0xbf553ec43f7b0000,0xbe483f6d3f0ebf35,0x3f0e3f6dbe48bf80,0x3f7b3ec4bf55bf35,0x3f55bec4bf7b0000,0x3e48bf6dbf0e3f35,
0xbf553ec43f7b8000,0xbe483f6d3f0ebf35,0x3f0e3f6dbe48bf80,0x3f7b3ec4bf55bf35,0x3f55bec4bf7b8000,0x3e48bf6dbf0e3f35,0xbf0ebf6d3e483f80,0xbf7bbec43f553f35,
0x3f27bf18bf6a3e48,0xbe2fbf80be893f62,0x3f1d3f67be60bf80,0x3f803e79bf65bf22,0xbea13f5c3f31bf0e,0x3f093f71bdfbbf7f,0xbf5fbf2c3f133f6d,0xbf6f3e163f7f3e95,
0xbf42bf4e3ecf3f7b,0xbf7cbd493f773ef1,0x3f4abedbbf7a8000,0x3cc9bf78bee63f46,0x3f733f04bf39bf55,0x3f58beacbf7ebdc9,0xbefc3f3e3f51bec4,0x3eb83f7d3d97bf75,
0x3f803e95bf5cbf35,0x3f18bf22bf673e48,0xbeacbf7fbe163f6d,0xbf78bef13f3e3f55,0xbf2cbf623e793f80,0xbf7dbdc93f713f0e,0xbedb3f463f4ebec4,0x3f043f75bd49bf7b,
0x3d49bf75bf043f35,0xbf4ebf463edb3f7b,0xbf713dc93f7d3ec4,0xbe793f623f2cbf0e,0xbf3e3ef13f788000,0x3e163f7f3eacbf55,0x3f673f22bf18bf6d,0x3f5cbe95bf80be48,
0x3f583f3ebee6bf7b,0x3f5fbe79bf80be95,0xbf6a3e163f7e3ec4,0xbd973f713f13bf22,0x3e2fbf67bf273f0e,0xbf4abf4e3eb83f7f,0x3f393f5cbe89bf80,0x3f73bd49bf7abef1,
0x3f09bf2cbf653e48,0xbefcbf78bcc93f75,0x3ecf3f7d3dfbbf6d,0x3f7f3eacbf51bf46,0xbf7cbedb3f423f55,0xbf1d3f183f6fbdc9,0x3f31bf04bf778000,0xbea1bf80be603f62,
0xbf46bf553e953f80,0xbf623e483f7f3ec4,0x3dc93f7b3ef1bf35,0x3f753f0ebf22bf6d,0x3f22bf0ebf750000,0xbef1bf7bbdc93f6d,0xbf7fbe483f623f35,0xbe953f553f46bec4,
0xbf223f0e3f758000,0x3ef13f7b3dc9bf6d,0x3f7f3e48bf62bf35,0x3e95bf55bf463ec4,0xbf46bf553e953f80,0xbf623e483f7f3ec4,0x3dc93f7b3ef1bf35,0x3f753f0ebf22bf6d,
0xbeb8bf80be893f55,0xbf7fbe793f583f46,0x3f513f4ebea1bf80,0x3f4abeacbf80be95,0x3f39bedbbf7ebe48,0xbee6bf7dbe2f3f62,0xbe603f5c3f42bec4,0x3f5f3f3ebecfbf7f,
0xbf6f3d493f773f0e,0x3d973f783f09bf22,0x3f13bf18bf738000,0xbf1dbf713cc93f75,0xbf31bf673dfb3f7b,0xbf653e163f7c3ef1,0x3f7a3f04bf27bf6d,0x3efcbf2cbf6a3dc9,
0xbe79bf7fbedb3f35,0xbf80be953f4e3f55,0xbe163f623f3ebec4,0x3f713f22bf04bf7b,0xbf5cbf463eac3f80,0xbf2c3ef13f7d3e48,0x3f183f753d49bf6d,0x3f67bdc9bf78bf0e,
0xbf78bdc93f673f35,0x3d493f753f18bf0e,0x3f7d3ef1bf2cbf6d,0x3eacbf46bf5c3e48,0xbf043f223f718000,0x3f3e3f62be16bf7b,0x3f4ebe95bf80bec4,0xbedbbf7fbe793f55,
0xbefcbf7dbe603f55,0xbf6a3d493f733f22,0x3f273f713cc9bf6d,0x3f51be79bf7ebef1,0xbf4abf5c3e2f3f7b,0xbf313edb3f7f3e95,0x3f653f3ebeb8bf80,0x3f09bf18bf77bdc9,
0xbf5f3e163f7a3f0e,0x3ecf3f803ea1bf46,0x3f42beacbf80bec4,0xbf13bf78bdfb3f62,0xbf1d3f043f7c3e48,0x3f393f67bd97bf75,0x3ee6bf2cbf6f8000,0xbf58bf4e3e893f7f,
0xbf6dbf353ec43f80,0xbec43f353f6d0000,0x3f6d3f35bec4bf80,0x3ec4bf35bf6d0000,0xbf6dbf353ec43f80,0xbec43f353f6d0000,0x3f6d3f35bec4bf80,0x3ec4bf35bf6d0000,
0xbec43f353f6d8000,0x3f6d3f35bec4bf80,0x3ec4bf35bf6d8000,0xbf6dbf353ec43f80,0xbec43f353f6d8000,0x3f6d3f35bec4bf80,0x3ec4bf35bf6d8000,0xbf6dbf353ec43f80,
0xbf7ebf043f133f7b,0xbcc93f673f42be95,0x3f733f2cbecfbf80,0x3e60bf4ebf5f3dc9,0xbf77be163f583f55,0x3eb83f803ee6bf22,0x3f7f3eacbf39bf6d,0xbe2fbf78bf1d3ef1,
0xbdfb3f5c3f51be48,0x3f803edbbf27bf75,0x3ea1bf3ebf6a8000,0xbf7abf183efc3f7f,0x3e893f7d3f09bf0e,0x3f6f3d49bf65bf46,0xbd97bf71bf313ec4,0xbf7cbe793f4a3f62,
0xbf5c3dc93f713f35,0x3f2c3f753e16bf55,0x3f18bef1bf80bec4,0xbf67bf463e793f7b,0xbf78bf223edb3f80,0xbd493f623f4ebe48,0x3f7d3e95bf3ebf6d,0xbeacbf7fbf043f0e,
0x3f043f7f3eacbf35,0x3f3ebe95bf7dbf0e,0xbf4ebf623d493f6d,0xbedb3f223f783e48,0xbe793f463f678000,0x3f803ef1bf18bf7b,0xbe16bf75bf2c3ec4,0xbf71bdc93f5c3f55,
0x3cc93f673f4abe48,0x3f733e16bf51bf62,0x3f09bf04bf7fbec4,0xbf77bf2c3eb83f7f,0xbf6abd493f5f3f55,0x3f273f783e60bf46,0x3f7c3f18bee6bf80,0xbdfbbf71bf393e95,
0x3f803edbbf1dbf7b,0xbea1bf7dbf133ef1,0xbf58bf5c3d973f6d,0xbe893f3e3f6f3dc9,0x3ecf3f803efcbf0e,0x3f42be79bf7abf22,0x3e2fbf4ebf658000,0xbf7ebeac3f313f75,
0xbf7fbf0e3ef13f80,0x3e953f7b3f22bec4,0x3f46be48bf75bf35,0xbf62bf553dc93f6d,0xbdc93f553f620000,0x3f753e48bf46bf6d,0xbf22bf7bbe953f35,0xbef13f0e3f7f3ec4,
0xbdc93f553f628000,0x3f753e48bf46bf6d,0xbf22bf7bbe953f35,0xbef13f0e3f7f3ec4,0x3f7f3f0ebef1bf80,0xbe95bf7bbf223ec4,0xbf463e483f753f35,0x3f623f55bdc9bf6d,
0xbf133edb3f7f3f0e,0x3f7e3f18becfbf7f,0x3f803f04befcbf80,0xbee6bf80bf093ef1,0x3f7a3f2cbea1bf7b,0xbe89bf78bf313e95,0xbeb8bf7dbf1d3ec4,0xbf273eac3f7c3f22,
0x3f513f673d97bf55,0x3dfbbf4ebf6abdc9,0x3cc9bf5cbf5f8000,0xbf65bd493f583f62,0x3e60bf3ebf73be48,0xbf77be793f393f75,0xbf6fbe163f4a3f6d,0x3f423f713e2fbf46,
0x3f3e3f753e79bf35,0x3e16bf46bf71be48,0xbf67bdc93f4e3f6d,0x3f5c3f623d49bf55,0xbf80bef13f043f80,0x3f183f7f3edbbf0e,0x3eacbf22bf7dbec4,0xbf78be953f2c3f7b,
0x3f2cbe95bf78bf35,0xbf7dbf223eac3f7b,0x3edb3f7f3f18bec4,0x3f04bef1bf80bf0e,0x3d493f623f5c8000,0x3f4ebdc9bf67bf55,0xbf71bf463e163f6d,0x3e793f753f3ebe48,
0x3ee6bf04bf80bf0e,0xbf7abeac3f1d3f7f,0xbf77bf3e3e2f3f6d,0x3ecf3f7d3f27be95,0xbd973f4e3f6f3e48,0x3f51bd49bf5fbf62,0x3f7e3edbbf09bf80,0xbf39bf78bea13f22,
0xbf65bf5cbcc93f55,0x3e603f713f4abdc9,0xbe893f2c3f7c3ec4,0x3f6a3e16bf42bf75,0x3f7f3f18beb8bf7b,0xbf13bf80befc3ef1,0xbdfbbf67bf588000,0xbf313e793f733f46,
0xbf7bbec43f0e3f80,0x3f553f6d3e48bf35,0xbe48bf6dbf550000,0xbf0e3ec43f7b3f35,0x3f7b3ec4bf0ebf80,0xbf55bf6dbe483f35,0x3e483f6d3f550000,0x3f0ebec4bf7bbf35,
0x3e483f6d3f558000,0x3f0ebec4bf7bbf35,0xbf7bbec43f0e3f80,0x3f553f6d3e48bf35,0xbe48bf6dbf558000,0xbf0e3ec43f7b3f35,0x3f7b3ec4bf0ebf80,0xbf55bf6dbe483f35,
0x3ee63f7d3f31be48,0x3e60bf2cbf7ebef1,0x3f773eacbf13bf80,0xbf6abf5cbd973f46,0xbf42bf78beb83f0e,0x3e2f3f673f5f3dc9,0xbf4a3d493f583f6d,0x3f803f18bea1bf75,
0x3f653e16bf39bf7b,0xbf7abf3e3dfb3f62,0xbe89bf71bf518000,0xbecf3f043f7f3f22,0xbf273e793f6f3f55,0x3f7c3edbbefcbf7f,0x3f1d3f803f09bec4,0x3cc9bf4ebf73be95,
0x3edbbef1bf7dbf35,0xbf5cbdc93f3e3f7b,0x3f803f22be79bf6d,0xbf4ebf75beac3f0e,0xbf71be953f183f80,0x3f783f46bd49bf55,0xbf2cbf7fbf043ec4,0x3e163f623f673e48,
0xbf67bf62be163f35,0x3f043f7f3f2cbe48,0x3d49bf46bf78bec4,0xbf183e953f713f55,0x3eac3f753f4e8000,0x3e79bf22bf80bf0e,0xbf3e3dc93f5c3f6d,0x3f7d3ef1bedbbf7b,
0xbf51bd493f423f7b,0x3f7e3f04beb8bf75,0x3cc93f4e3f773ec4,0x3ee6bedbbf7abf46,0x3f583f713ea1bf0e,0xbefcbf7dbf393dc9,0x3f6a3e79bf1dbf80,0xbf7fbf2c3e2f3f62,
0x3f133f803f27be48,0xbdfbbf5cbf6fbe95,0x3f803f18be89bf6d,0xbf65bf67be603f22,0x3f09beacbf73bf55,0xbf5fbe163f313f7f,0xbecfbf78bf4a8000,0xbd973f3e3f7c3ef1,
0xbf62be483f223f80,0x3f7f3f0ebe95bf6d,0xbf75bf55bdc93f35,0x3f463f7b3ef1bec4,0xbef1bf7bbf460000,0x3dc93f553f753ec4,0x3e95bf0ebf7fbf35,0xbf223e483f623f6d,
0x3ef13f7b3f468000,0xbdc9bf55bf75bec4,0xbe953f0e3f7f3f35,0x3f22be48bf62bf6d,0xbf62be483f223f80,0x3f7f3f0ebe95bf6d,0xbf75bf55bdc93f35,0x3f463f7b3ef1bec4,
0x3f803f2cbdfbbf55,0xbf73bf5cbe2f3f22,0x3f583e16bf27bf80,0xbf77bedb3ecf3f75,0x3eb83f713f5f3e48,0xbd97bf4ebf7abef1,0x3f513f783ee6bec4,0xbf1dbf80bf313dc9,
0x3cc9bf3ebf7ebf0e,0xbea13f043f7c3f46,0xbf09bf7dbf428000,0x3e893f673f6a3e95,0x3f6f3eacbefcbf7b,0xbf7fbf183e603f62,0x3f13be79bf65bf6d,0xbf4abd493f393f7f,
0xbf7dbf46bd493f35,0x3f713f623e79bf0e,0xbf5cbf75bedb3ec4,0x3f3e3f7f3f18be48,0xbf4ebdc93f2c3f80,0x3f673e95bf04bf7b,0xbf78bef13eac3f6d,0x3f803f22be16bf55,
0xbe163f223f803f35,0x3eacbef1bf78bf55,0xbf043e953f673f6d,0x3f2cbdc9bf4ebf7b,0x3f183f7f3f3e8000,0xbedbbf75bf5cbe48,0x3e793f623f713ec4,0xbd49bf46bf7dbf0e,
0x3f7e3f18be2fbf55,0xbf80bf2c3d973f46,0x3f733edbbeb8bf6d,0xbf7abf043e893f62,0x3f5f3e79bf09bf7b,0xbf6abeac3ee63f75,0x3f423d49bf31bf80,0xbf51be163f1d3f7f,
0xbdfbbf4ebf7cbf0e,0x3cc93f3e3f7f3f22,0xbea1bf67bf6fbec4,0x3e603f5c3f773ef1,0xbefcbf78bf58be48,0x3ecf3f713f653e95,0xbf27bf80bf398000,0x3f133f7d3f4a3dc9,
0x3f350000bf353f80,0xbf3500003f35bf80,0x3f350000bf353f80,0xbf3500003f35bf80,0x3f350000bf353f80,0xbf3500003f35bf80,0x3f350000bf353f80,0xbf3500003f35bf80,
0xbf353f80bf358000,0x3f35bf803f358000,0xbf353f80bf358000,0x3f35bf803f358000,0xbf353f80bf358000,0x3f35bf803f358000,0xbf353f80bf358000,0x3f35bf803f358000,
0x3f5f3f04bf58bf0e,0x3f6a3edbbf65bef1,0x3f423f2cbf39bf35,0x3f513f18bf4abf22,0x3f7e3e16bf7cbe48,0x3f803d49bf7fbdc9,0x3f733eacbf6fbec4,0x3f7a3e79bf77be95,
0x3efcbf5cbf093f55,0x3ecfbf67bee63f62,0x3f27bf3ebf313f35,0x3f13bf4ebf1d3f46,0x3dfbbf7dbe2f3f7b,0x3cc9bf80bd973f7f,0x3ea1bf71beb83f6d,0x3e60bf78be893f75,
0xbf183f463f2cbf35,0xbedb3f623f04bf55,0xbe793f753eacbf6d,0xbd493f7f3e16bf7b,0xbf7d3dc93f800000,0xbf713e953f78be48,0xbf5c3ef13f67bec4,0xbf3e3f223f4ebf0e,
0x3f4e3f22bf3ebf35,0x3f673ef1bf5cbf0e,0x3f783e95bf71bec4,0x3f803dc9bf7dbe48,0x3e163f7fbd49bf80,0x3eac3f75be79bf7b,0x3f043f62bedbbf6d,0x3f2c3f46bf18bf55,
0xbf6fbedb3f5f3f0e,0xbf7fbe163f7a3e95,0xbf13bf5c3ee63f6d,0xbf4abf2c3f313f46,0xbcc9bf80bdfb3f7b,0xbea1bf783e2f3f7f,0x3f09bf4ebf273f35,0x3e89bf71becf3f62,
0xbeb83f673efcbf55,0xbd973f7d3e60bf75,0xbf513f043f65bec4,0xbf1d3f3e3f39bf22,0xbf80bd493f7e3e48,0xbf733e793f7cbdc9,0xbf58bf183f423f35,0xbf77beac3f6a3ef1,
0x3e953f7bbdc9bf80,0x3f223f55bef1bf6d,0x3f623f0ebf46bf35,0x3f7f3e48bf75bec4,0x3f75be48bf7f0000,0x3f46bf0ebf623ec4,0x3ef1bf55bf223f35,0x3dc9bf7bbe953f6d,
0x3f75be48bf7f8000,0x3f46bf0ebf623ec4,0x3ef1bf55bf223f35,0x3dc9bf7bbe953f6d,0xbe95bf7b3dc93f80,0xbf22bf553ef13f6d,0xbf62bf0e3f463f35,0xbf7fbe483f753ec4,
0xbf583edb3f73be48,0xbefc3f4e3f31bf22,0xbf6abf043f4a3f35,0xbf7fbd493f7c3e95,0x3f513f2cbf27bf55,0x3f7e3e79bf6fbef1,0xbcc93f7d3e89bf6d,0x3ee63f71be60bf7f,
0x3f093f67bea1bf7b,0x3f5f3f18bf39bf46,0xbecf3f5c3f1dbf35,0x3d973f803e2fbf75,0x3f13bf3ebf423f0e,0x3dfbbf78beb83f62,0x3f803e16bf77bec4,0x3f65beacbf7a3dc9,
0xbf71bef13f4e3f35,0xbf783dc93f803e48,0xbf2c3f223f5cbec4,0xbe163f753edbbf55,0x3f67be95bf7d0000,0x3f04bf46bf3e3f0e,0xbd49bf7fbe793f6d,0xbf18bf623eac3f7b,
0xbeac3f623f18bf35,0x3e793f7f3d49bf7b,0x3f3e3f46bf04bf6d,0x3f7d3e95bf67bf0e,0xbedbbf753e163f80,0xbf5cbf223f2c3f55,0xbf80bdc93f783ec4,0xbf4e3ef13f71be48,
0xbf27bf5c3eb83f7b,0xbf7cbeac3f5f3f22,0x3f1dbf2cbf583ec4,0xbcc9bf7dbea13f62,0x3f653f18bf31bf55,0x3f7abd49bf7ebe95,0xbe893f673f13bf35,0x3ecf3f78bd97bf7f,
0xbf423f043f6fbe48,0xbe2f3f713efcbf46,0xbf4abf3e3f093f6d,0xbf80be163f733ef1,0x3ee6bf4ebf393f0e,0xbe60bf80bdfb3f75,0x3f773edbbf51bf35,0x3f6abe79bf7fbdc9,
0xbf0ebf6d3e483f80,0xbf7bbec43f553f35,0xbf553ec43f7b0000,0xbe483f6d3f0ebf35,0x3f0e3f6dbe48bf80,0x3f7b3ec4bf55bf35,0x3f55bec4bf7b0000,0x3e48bf6dbf0e3f35,
0xbf553ec43f7b8000,0xbe483f6d3f0ebf35,0x3f0e3f6dbe48bf80,0x3f7b3ec4bf55bf35,0x3f55bec4bf7b8000,0x3e48bf6dbf0e3f35,0xbf0ebf6d3e483f80,0xbf7bbec43f553f35,
0xbd97bf7dbeb83f55,0xbf51bf3e3efc3f75,0x3f7e3eacbf58bf35,0x3f39bf04bf733dc9,0x3ee63f78bcc9bf7b,0x3f7a3edbbf4abf46,0xbf773d493f7c3ec4,0xbecf3f4e3f42bef1,
0xbf7fbe163f6f3f0e,0xbf133f2c3f5fbe95,0x3dfbbf71bf093f35,0xbf31bf5c3ea13f7f,0x3f65be79bf80be48,0x3e60bf67bf1d3f22,0x3e893f803e2fbf6d,0x3f6a3f18bf27bf62,
0x3d49bf75bf043f35,0xbf4ebf463edb3f7b,0xbf713dc93f7d3ec4,0xbe793f623f2cbf0e,0xbf3e3ef13f780000,0x3e163f7f3eacbf55,0x3f673f22bf18bf6d,0x3f5cbe95bf80be48,
0xbf80be953f5c3f35,0xbf183f223f67be48,0x3eac3f7f3e16bf6d,0x3f783ef1bf3ebf55,0x3f2c3f62be79bf80,0x3f7d3dc9bf71bf0e,0x3edbbf46bf4e3ec4,0xbf04bf753d493f7b,
0xbe60bf80bea13f55,0xbf77bf043f313f62,0x3f6f3f18bf1dbf6d,0x3f42bedbbf7cbdc9,0xbf513eac3f7f3e48,0x3dfb3f7d3ecfbf46,0xbcc9bf78befc3f35,0xbf65bf2c3f093f75,
0xbf7abd493f733f0e,0xbe893f5c3f39bef1,0x3eb8bf4ebf4a3ec4,0xbf27bf673e2f3f7f,0x3f133f71bd97bf7b,0x3f7e3e16bf6abf22,0xbf80be793f5f3f35,0xbee63f3e3f58be95,
0x3f463f55be95bf80,0x3f62be48bf7fbec4,0xbdc9bf7bbef13f35,0xbf75bf0e3f223f6d,0xbf223f0e3f750000,0x3ef13f7b3dc9bf6d,0x3f7f3e48bf62bf35,0x3e95bf55bf463ec4,
0x3f22bf0ebf758000,0xbef1bf7bbdc93f6d,0xbf7fbe483f623f35,0xbe953f553f46bec4,0x3f463f55be95bf80,0x3f62be48bf7fbec4,0xbdc9bf7bbef13f35,0xbf75bf0e3f223f6d,
0x3f6a3f2cbefcbf7b,0x3f27bf04bf7abdc9,0xbf7cbe163f653f35,0xbdfb3f673f31bef1,0xbcc93f713f1dbf0e,0x3f733f18bf13bf75,0xbf09bf78bd973f6d,0xbf77bd493f6f3f22,
0x3ecfbf3ebf5f3e48,0xbf42bf5c3e603f7f,0x3e2f3f7d3ee6bf35,0x3f7e3edbbf39bf62,0x3f803eacbf4abf55,0x3ea1bf4ebf513e95,0xbf583e793f7f3ec4,0x3e893f803eb8bf46,
0x3f783dc9bf67bf35,0xbd49bf75bf183f0e,0xbf7dbef13f2c3f6d,0xbeac3f463f5cbe48,0x3f04bf22bf710000,0xbf3ebf623e163f7b,0xbf4e3e953f803ec4,0x3edb3f7f3e79bf55,
0xbe79bf7fbedb3f35,0xbf80be953f4e3f55,0xbe163f623f3ebec4,0x3f713f22bf04bf7b,0xbf5cbf463eac3f80,0xbf2c3ef13f7d3e48,0x3f183f753d49bf6d,0x3f67bdc9bf78bf0e,
0x3e89bf4ebf583e48,0xbf6fbf2c3ee63f7f,0xbd973f673f39bec4,0x3f7c3f04bf1dbf75,0xbdfbbf78bf133f0e,0xbf80beac3f423f62,0x3ea13f803ecfbf35,0x3f7a3e16bf5fbf46,
0xbf77bf183f093f7b,0xbeb83f3e3f65bdc9,0x3f7f3edbbf31bf6d,0x3e2fbf5cbf4a3e95,0xbf7ebe793f513f55,0x3cc93f713f27bef1,0x3f733d49bf6abf35,0xbe60bf7dbefc3f22,
0xbf6dbf353ec43f80,0xbec43f353f6d0000,0x3f6d3f35bec4bf80,0x3ec4bf35bf6d0000,0xbf6dbf353ec43f80,0xbec43f353f6d0000,0x3f6d3f35bec4bf80,0x3ec4bf35bf6d0000,
0xbec43f353f6d8000,0x3f6d3f35bec4bf80,0x3ec4bf35bf6d8000,0xbf6dbf353ec43f80,0xbec43f353f6d8000,0x3f6d3f35bec4bf80,0x3ec4bf35bf6d8000,0xbf6dbf353ec43f80,
0xbf4a3e793f7c3f0e,0x3f313f713d97bf62,0x3f65bd49bf6fbf35,0xbf09bf7dbe893f46,0xbefc3f183f7a3e48,0x3f6a3f3ebea1bf7f,0x3f27bedbbf80bec4,0xbf51bf5c3dfb3f75,
0x3f1d3f783e2fbf55,0x3f39beacbf7fbef1,0xbee6bf80beb83f35,0xbf583e163f773f22,0x3f5f3f4ebe60bf7b,0x3ecfbf2cbf73bdc9,0xbf42bf673cc93f6d,0xbf133f043f7e3e95,
0x3f043f7f3eacbf35,0x3f3ebe95bf7dbf0e,0xbf4ebf623d493f6d,0xbedb3f223f783e48,0xbe793f463f670000,0x3f803ef1bf18bf7b,0xbe16bf75bf2c3ec4,0xbf71bdc93f5c3f55,
0x3f5cbdc9bf71bf35,0xbf2cbf75be163f55,0xbf183ef13f803ec4,0x3f673f46be79bf7b,0x3f783f22bedbbf80,0x3d49bf62bf4e3e48,0xbf7dbe953f3e3f6d,0x3eac3f7f3f04bf0e,
0x3f31beacbf7ebf0e,0xbf65bf4e3e2f3f75,0xbf7abe793f423f6d,0x3efc3f803ecfbf22,0x3f6f3f3ebe89bf7b,0x3d97bf5cbf583dc9,0xbf13bf7dbea13f35,0xbf1d3edb3f803ef1,
0xbf39bf71bdfb3f55,0xbee63f183f7c3e95,0x3e603f783f27bec4,0x3f5fbd49bf6abf46,0x3eb8bf2cbf77be48,0xbf7fbf043f093f7f,0xbf513e163f733f35,0x3f4a3f673cc9bf62,
0x3f7f3f0ebef1bf80,0xbe95bf7bbf223ec4,0xbf463e483f753f35,0x3f623f55bdc9bf6d,0x3dc9bf55bf620000,0xbf75be483f463f6d,0x3f223f7b3e95bf35,0x3ef1bf0ebf7fbec4,
0x3dc9bf55bf628000,0xbf75be483f463f6d,0x3f223f7b3e95bf35,0x3ef1bf0ebf7fbec4,0xbf7fbf0e3ef13f80,0x3e953f7b3f22bec4,0x3f46be48bf75bf35,0xbf62bf553dc93f6d,
0xbe2fbf71bf423e48,0xbf4a3e163f6f3f46,0xbf393e793f773f35,0x3f733f3ebe60bf75,0xbf583d493f653f55,0x3f5f3f5cbcc9bf62,0x3f6a3f4ebdfbbf6d,0xbd97bf67bf513dc9,
0xbf7cbeac3f273f7b,0x3f1d3f7d3eb8bf22,0x3f313f783e89bf35,0x3ea1bf2cbf7abe95,0x3f093f803ee6bf0e,0x3efcbf04bf80bef1,0x3ecfbf18bf7ebec4,0xbf7fbedb3f133f7f,
0xbf2c3e953f783f35,0x3f7d3f22beacbf7b,0xbedbbf7fbf183ec4,0xbf043ef13f803f0e,0xbd49bf62bf5c0000,0xbf4e3dc93f673f55,0x3f713f46be16bf6d,0xbe79bf75bf3e3e48,
0x3f3e3f753e79bf35,0x3e16bf46bf71be48,0xbf67bdc93f4e3f6d,0x3f5c3f623d49bf55,0xbf80bef13f043f80,0x3f183f7f3edbbf0e,0x3eacbf22bf7dbec4,0xbf78be953f2c3f7b,
0x3f733e79bf31bf7b,0xbf58bf67bdfb3f46,0xbefcbf80bf133ec4,0xbeb83f183f7f3ef1,0xbf423e163f6a3f55,0x3f7c3f2cbe89bf75,0x3f4a3f713e60bf35,0xbcc9bf5cbf65bdc9,
0xbea1bf78bf393e48,0xbf093edb3f7e3f22,0xbf5fbd493f513f6d,0x3f6f3f4ebd97bf62,0x3f273f7d3ecfbf0e,0x3e2fbf3ebf77be95,0x3f1dbeacbf7abf35,0xbf80bf043ee63f7f,
0xbf7bbec43f0e3f80,0x3f553f6d3e48bf35,0xbe48bf6dbf550000,0xbf0e3ec43f7b3f35,0x3f7b3ec4bf0ebf80,0xbf55bf6dbe483f35,0x3e483f6d3f550000,0x3f0ebec4bf7bbf35,
0x3e483f6d3f558000,0x3f0ebec4bf7bbf35,0xbf7bbec43f0e3f80,0x3f553f6d3e48bf35,0xbe48bf6dbf558000,0xbf0e3ec43f7b3f35,0x3f7b3ec4bf0ebf80,0xbf55bf6dbe483f35,
0x3f733f4ebcc9bf55,0xbf09bf80bf1d3e95,0x3efcbedbbf7cbf35,0xbf6fbe793f273f7f,0xbf7fbf043ecf3f7b,0x3f513f713e89bf22,0xbdfb3f3e3f7a3ec4,0x3f39be16bf65bf62,
0x3ea1bf18bf80bf0e,0xbf58bd493f4a3f75,0xbf5fbf67be2f3f35,0x3eb83f783f42bdc9,0x3d973f5c3f6a3e48,0x3f13beacbf77bf46,0x3f7e3f2cbe60bf6d,0xbf31bf7dbee63ef1,
0xbf67bf62be163f35,0x3f043f7f3f2cbe48,0x3d49bf46bf78bec4,0xbf183e953f713f55,0x3eac3f753f4e0000,0x3e79bf22bf80bf0e,0xbf3e3dc93f5c3f6d,0x3f7d3ef1bedbbf7b,
0xbedb3ef13f7d3f35,0x3f5c3dc9bf3ebf7b,0xbf80bf223e793f6d,0x3f4e3f753eacbf0e,0x3f713e95bf18bf80,0xbf78bf463d493f55,0x3f2c3f7f3f04bec4,0xbe16bf62bf67be48,
0x3f7c3f3ebd97bf55,0xbf4abf78becf3ef1,0x3f31be16bf5fbf6d,0xbf73beac3f093f7f,0xbe60bf67bf65be48,0xbe893f183f803f22,0xbf6fbf5cbdfb3f35,0x3f273f803f13be95,
0x3e2fbf2cbf7fbf0e,0xbf1d3e793f6a3f62,0xbf39bf7dbefc3ec4,0x3ea13f713f583dc9,0xbf7abedb3ee63f7b,0x3f773f4e3cc9bf46,0xbeb83f043f7e3f35,0x3f42bd49bf51bf75,
0x3f623e48bf22bf80,0xbf7fbf0e3e953f6d,0x3f753f553dc9bf35,0xbf46bf7bbef13ec4,0x3ef13f7b3f460000,0xbdc9bf55bf75bec4,0xbe953f0e3f7f3f35,0x3f22be48bf62bf6d,
0xbef1bf7bbf468000,0x3dc93f553f753ec4,0x3e95bf0ebf7fbf35,0xbf223e483f623f6d,0x3f623e48bf22bf80,0xbf7fbf0e3e953f6d,0x3f753f553dc9bf35,0xbf46bf7bbef13ec4,
0xbf393d493f4a3f7b,0x3f653e79bf13bf7f,0xbe603f183f7f3f35,0x3efcbeacbf6fbf62,0xbf6abf67be893f0e,0x3f423f7d3f09be95,0xbf7cbf043ea13f6d,0x3f7e3f3ebcc9bf46,
0x3f313f803f1dbe48,0xbee6bf78bf51bdc9,0x3f7a3f4e3d97bf35,0xbf5fbf71beb83ef1,0xbecf3edb3f773f55,0x3f27be16bf58bf75,0x3e2f3f5c3f733ec4,0x3dfbbf2cbf80bf22,
0x3e16bf22bf80bf35,0xbeac3ef13f783f55,0x3f04be95bf67bf6d,0xbf2c3dc93f4e3f7b,0xbf18bf7fbf3e0000,0x3edb3f753f5c3e48,0xbe79bf62bf71bec4,0x3d493f463f7d3f0e,
0xbf7dbf46bd493f35,0x3f713f623e79bf0e,0xbf5cbf75bedb3ec4,0x3f3e3f7f3f18be48,0xbf4ebdc93f2c3f80,0x3f673e95bf04bf7b,0xbf78bef13eac3f6d,0x3f803f22be16bf55,
0x3f4a3f7d3f13be48,0xbf39bf80bf273dc9,0x3f653f713ecfbec4,0xbf58bf78befc3e95,0x3f773f5c3e60bf0e,0xbf6fbf67bea13ef1,0x3f7f3f3e3cc9bf35,0xbf7cbf4ebdfb3f22,
0x3f1dbe16bf51bf7b,0xbf313d493f423f7f,0x3ee6beacbf6abf6d,0xbf093e793f5f3f75,0x3e89bf04bf7abf55,0xbeb83edb3f733f62,0x3d97bf2cbf80bf35,0xbe2f3f183f7e3f46,
0x3f003f003f003f00,0x3f003f003f003f00,0x3f003f003f003f00,0x3f003f003f003f00,0x3f003f003f003f00,0x3f003f003f003f00,0x3f003f003f003f00,0x3f003f003f003f00,
0xbf003f00bf003f00,0xbf003f00bf003f00,0xbf003f00bf003f00,0xbf003f00bf003f00,0xbf003f00bf003f00,0xbf003f00bf003f00,0xbf003f00bf003f00,0xbf003f00bf003f00,
0x3e893e793e603e48,0x3eb83eac3ea13e95,0x3d973d493cc90000,0x3e2f3e163dfb3dc9,0x3f1d3f183f133f0e,0x3f313f2c3f273f22,0x3ee63edb3ecf3ec4,0x3f093f043efc3ef1,
0x3f773f783f7a3f7b,0x3f6f3f713f733f75,0x3f7f3f803f803f80,0x3f7c3f7d3f7e3f7f,0x3f4a3f4e3f513f55,0x3f393f3e3f423f46,0x3f653f673f6a3f6d,0x3f583f5c3f5f3f62,
0xbf18bf22bf2cbf35,0xbedbbef1bf04bf0e,0xbe79be95beacbec4,0xbd49bdc9be16be48,0xbf7dbf7fbf80bf80,0xbf71bf75bf78bf7b,0xbf5cbf62bf67bf6d,0xbf3ebf46bf4ebf55,
0x3f4e3f463f3e3f35,0x3f673f623f5c3f55,0x3f783f753f713f6d,0x3f803f7f3f7d3f7b,0x3e163dc93d498000,0x3eac3e953e793e48,0x3f043ef13edb3ec4,0x3f2c3f223f183f0e,
0xbf6abf71bf77bf7b,0xbf42bf4ebf58bf62,0xbf7cbf78bf73bf6d,0xbf7ebf80bf80bf7f,0xbf39bf2cbf1dbf0e,0xbf65bf5cbf51bf46,0xbe60be16bd970000,0xbefcbedbbeb8be95,
0x3ecf3eac3e893e48,0x3f273f183f093ef1,0xbe2fbe79bea1bec4,0x3dfb3d49bcc9bdc9,0xbf31bf3ebf4abf55,0xbee6bf04bf13bf22,0xbf7abf7dbf7fbf80,0xbf5fbf67bf6fbf75,
0x3f753f7b3f7f3f80,0x3f463f553f623f6d,0x3ef13f0e3f223f35,0x3dc93e483e953ec4,0xbe95be48bdc90000,0xbf22bf0ebef1bec4,0xbf62bf55bf46bf35,0xbf7fbf7bbf75bf6d,
0xbe95be48bdc98000,0xbf22bf0ebef1bec4,0xbf62bf55bf46bf35,0xbf7fbf7bbf75bf6d,0xbf75bf7bbf7fbf80,0xbf46bf55bf62bf6d,0xbef1bf0ebf22bf35,0xbdc9be48be95bec4,
0x3f7a3f713f653f55,0x3f773f7d3f803f7f,0x3eb83e793dfb0000,0x3f423f2c3f133ef1,0xbe2fbd493d973e48,0xbf1dbf04becfbe95,0x3f393f4e3f5f3f6d,0x3ea13edb3f093f22,
0x3e603eac3ee63f0e,0xbe89be16bcc93dc9,0x3f6f3f783f7e3f80,0x3f273f3e3f513f62,0xbf7cbf80bf7fbf7b,0xbf4abf5cbf6abf75,0xbf31bf18befcbec4,0xbf73bf67bf58bf46,
0x3f713f623f4e3f35,0x3f783f7f3f803f7b,0x3f2c3f463f5c3f6d,0x3e163e953edb3f0e,0xbf67bf75bf7dbf80,0xbf04bf22bf3ebf55,0x3d49bdc9be79bec4,0x3f183ef13eac3e48,
0x3eac3ef13f183f35,0xbe79bdc93d493e48,0xbf3ebf22bf04bec4,0xbf7dbf75bf67bf55,0x3edb3e953e168000,0x3f5c3f463f2c3f0e,0x3f803f7f3f783f6d,0x3f4e3f623f713f7b,
0x3f7f3f783f6a3f55,0x3f513f673f773f7f,0x3dfbbd49be60bec4,0x3f393f183ee63e95,0xbf73bf7dbf80bf7b,0xbf09bf2cbf4abf62,0xbefcbeacbe2f0000,0xbf6fbf5cbf42bf22,
0x3d973e793ecf3f0e,0xbf13bedbbe89bdc9,0x3f7e3f803f7a3f6d,0x3f313f4e3f653f75,0x3ea13e16bcc9be48,0x3f583f3e3f1d3ef1,0xbf5fbf71bf7cbf80,0xbeb8bf04bf27bf46,
0x3f553f6d3f7b3f80,0x3e483ec43f0e3f35,0xbf0ebec4be480000,0xbf7bbf6dbf55bf35,0xbf55bf6dbf7bbf80,0xbe48bec4bf0ebf35,0x3f0e3ec43e480000,0x3f7b3f6d3f553f35,
0xbf0ebec4be488000,0xbf7bbf6dbf55bf35,0xbf55bf6dbf7bbf80,0xbe48bec4bf0ebf35,0x3f0e3ec43e488000,0x3f7b3f6d3f553f35,0x3f553f6d3f7b3f80,0x3e483ec43f0e3f35,
0x3f273f4e3f6a3f7b,0xbe2f3d493e893ef1,0x3f1d3edb3e600000,0x3f803f783f653f46,0xbea1bf04bf31bf55,0x3f093eac3dfbbdc9,0xbf5fbf3ebf13bec4,0xbf6fbf7dbf7fbf75,
0xbf42bf18becfbe48,0xbf7cbf80bf77bf62,0x3f4a3f673f7a3f80,0x3cc93e793ee63f22,0x3f733f5c3f393f0e,0x3f583f713f7e3f7f,0xbefcbf2cbf51bf6d,0x3eb83e16bd97be95,
0x3d493e953f043f35,0xbf4ebf22bedbbe48,0xbf71bf7fbf7dbf6d,0xbe79bef1bf2cbf55,0xbf3ebf62bf78bf80,0x3e16bdc9beacbf0e,0x3f673f463f183ec4,0x3f5c3f753f803f7b,
0xbf80bf75bf5cbf35,0xbf18bf46bf67bf7b,0x3eac3dc9be16bec4,0x3f783f623f3e3f0e,0x3f2c3ef13e798000,0x3f7d3f7f3f713f55,0x3edb3f223f4e3f6d,0xbf04be95bd493e48,
0xbf58bf2cbee6be48,0xbf5fbf78bf80bf75,0x3f6a3f7d3f7e3f6d,0x3d973eac3f133f46,0xbe2fbedbbf27bf55,0x3f4a3f183eb83dc9,0xbf39bf04be890000,0xbf73bf80bf7abf62,
0xbf09bf3ebf65bf7b,0x3efc3e79bcc9be95,0xbecfbe163dfb3ec4,0xbf7fbf71bf51bf22,0x3f7c3f673f423f0e,0x3f1d3f4e3f6f3f7f,0xbf31bf5cbf77bf80,0x3ea13d49be60bef1,
0x3f223f553f753f80,0xbef1be483dc93ec4,0xbf7fbf7bbf62bf35,0xbe95bf0ebf46bf6d,0x3f463f0e3e950000,0x3f623f7b3f7f3f6d,0xbdc93e483ef13f35,0xbf75bf55bf22bec4,
0xbf46bf0ebe958000,0xbf62bf7bbf7fbf6d,0x3dc9be48bef1bf35,0x3f753f553f223ec4,0x3f223f553f753f80,0xbef1be483dc93ec4,0xbf7fbf7bbf62bf35,0xbe95bf0ebf46bf6d,
0xbeb8bd493e893f0e,0xbf7fbf78bf58bf22,0x3f513f183ea10000,0x3f4a3f713f803f75,0x3f393f673f7e3f7b,0xbee6be163e2f3ef1,0xbe60bf04bf42bf6d,0x3f5f3f2c3ecf3dc9,
0xbf6fbf80bf77bf55,0x3d97be79bf09bf46,0x3f133f4e3f733f80,0xbf1dbeacbcc93e95,0xbf31bedbbdfb3e48,0xbf65bf7dbf7cbf62,0x3f7a3f5c3f273ec4,0x3efc3f3e3f6a3f7f,
0xbf78bf7fbf67bf35,0x3d49be95bf18bf55,0x3f7d3f623f2c3ec4,0x3eac3f223f5c3f7b,0xbf04bf46bf71bf80,0x3f3e3ef13e16be48,0x3f4e3f753f803f6d,0xbedbbdc93e793f0e,
0x3e79bdc9bedbbf35,0x3f803f753f4e3f0e,0x3e163ef13f3e3f6d,0xbf71bf46bf04be48,0x3f5c3f223eac8000,0x3f2c3f623f7d3f7b,0xbf18be953d493ec4,0xbf67bf7fbf78bf55,
0x3efc3e16be60bf0e,0x3f6a3f803f733f46,0xbf27beac3cc93ec4,0xbf51bf78bf7ebf62,0x3f4a3f043e2fbe48,0x3f313f673f7f3f75,0xbf65bf2cbeb80000,0xbf09bf4ebf77bf7f,
0x3f5f3f7d3f7a3f55,0xbecfbd493ea13f22,0xbf42bf71bf80bf6d,0x3f133e79bdfbbef1,0x3f1d3f5c3f7c3f7b,0xbf39bedbbd973e95,0xbee6bf3ebf6fbf80,0x3f583f183e89bdc9,
0x3ec43f353f6d3f80,0xbf6dbf35bec40000,0xbec4bf35bf6dbf80,0x3f6d3f353ec40000,0x3ec43f353f6d3f80,0xbf6dbf35bec40000,0xbec4bf35bf6dbf80,0x3f6d3f353ec40000,
0xbf6dbf35bec48000,0xbec4bf35bf6dbf80,0x3f6d3f353ec48000,0x3ec43f353f6d3f80,0xbf6dbf35bec48000,0xbec4bf35bf6dbf80,0x3f6d3f353ec48000,0x3ec43f353f6d3f80,
0xbf7ebf5cbf13be48,0xbcc9bedbbf42bf75,0x3f733f3e3ecf0000,0x3e603f183f5f3f7f,0xbf77bf7dbf58bf0e,0x3eb8bd49bee6bf46,0x3f7f3f713f393ec4,0xbe2f3e793f1d3f62,
0xbdfbbf04bf51bf7b,0x3f803f673f273e95,0x3ea13f2c3f6a3f80,0xbf7abf4ebefcbdc9,0x3e89be16bf09bf55,0x3f6f3f803f653f22,0xbd973eac3f313f6d,0xbf7cbf78bf4abef1,
0x3f043dc9beacbf35,0x3f3e3f753f7d3f55,0xbf4ebef1bd493ec4,0xbedbbf46bf78bf7b,0xbe79bf22bf67bf80,0x3f803f623f183e48,0xbe163e953f2c3f6d,0xbf71bf7fbf5cbf0e,
0x3f5c3f7f3f713f35,0xbf2cbe953e163f0e,0xbf18bf62bf80bf6d,0x3f673f223e79be48,0x3f783f463edb8000,0x3d493ef13f4e3f7b,0xbf7dbf75bf3ebec4,0x3eacbdc9bf04bf55,
0xbcc93edb3f4a3f7b,0xbf73bf7dbf51bef1,0xbf09bf5cbf7fbf6d,0x3f773f3e3eb8bdc9,0x3f6a3f803f5f3f0e,0xbf27be793e603f22,0xbf7cbf4ebee60000,0x3dfbbeacbf39bf75,
0xbf80bf67bf1dbe48,0x3ea1be16bf13bf62,0x3f583f043d97bec4,0x3e893f2c3f6f3f7f,0xbecf3d493efc3f55,0xbf42bf78bf7abf46,0xbe2fbf18bf65bf80,0x3f7e3f713f313e95,
0x3dc93f0e3f623f80,0xbf75bf7bbf46bec4,0x3f223e48be95bf35,0x3ef13f553f7f3f6d,0xbf7fbf55bef10000,0x3e95be48bf22bf6d,0x3f463f7b3f753f35,0xbf62bf0ebdc93ec4,
0xbf7fbf55bef18000,0x3e95be48bf22bf6d,0x3f463f7b3f753f35,0xbf62bf0ebdc93ec4,0xbdc9bf0ebf62bf80,0x3f753f7b3f463ec4,0xbf22be483e953f35,0xbef1bf55bf7fbf6d,
0xbf13bf67bf7fbf55,0x3f7e3f4e3ecfbdc9,0x3f803f5c3efc0000,0xbee63d493f093f62,0x3f7a3f3e3ea1be48,0xbe893e793f313f75,0xbeb83e163f1d3f6d,0xbf27bf71bf7cbf46,
0x3f513edbbd97bf0e,0x3dfb3f183f6a3f7f,0x3cc93f043f5f3f80,0xbf65bf80bf58bef1,0x3e603f2c3f733f7b,0xbf77bf78bf39be95,0xbf6fbf7dbf4abec4,0x3f423eacbe2fbf22,
0x3f2c3f753f783f35,0xbf7dbf46beac3e48,0x3edbbdc9bf18bf6d,0x3f043f623f803f55,0x3d49bef1bf5cbf80,0x3f4e3f7f3f673f0e,0xbf71bf22be163ec4,0x3e79be95bf3ebf7b,
0xbf3ebe953e793f35,0xbe16bf22bf71bf7b,0x3f673f7f3f4e3ec4,0xbf5cbef13d493f0e,0x3f803f623f048000,0xbf18bdc93edb3f55,0xbeacbf46bf7dbf6d,0x3f783f753f2c3e48,
0xbee6bf5cbf80bf55,0x3f7a3f713f1d3dc9,0x3f773f2c3e2fbec4,0xbecf3e163f273f75,0x3d973f183f6f3f7b,0xbf51bf80bf5fbef1,0xbf7ebf67bf090000,0x3f393e79bea1bf46,
0x3f653f04bcc9bf0e,0xbe603eac3f4a3f7f,0x3e893f3e3f7c3f6d,0xbf6abf7dbf42be95,0xbf7fbf4ebeb83e48,0x3f133d49befcbf62,0x3dfbbedbbf58bf80,0x3f313f783f733f22,
0xbe483ec43f553f80,0xbf0ebf6dbf7bbf35,0x3f7b3f6d3f0e0000,0xbf55bec43e483f35,0x3e48bec4bf55bf80,0x3f0e3f6d3f7b3f35,0xbf7bbf6dbf0e0000,0x3f553ec4be48bf35,
0xbf7bbf6dbf0e8000,0x3f553ec4be48bf35,0xbe483ec43f553f80,0xbf0ebf6dbf7bbf35,0x3f7b3f6d3f0e8000,0xbf55bec43e483f35,0x3e48bec4bf55bf80,0x3f0e3f6d3f7b3f35,
0x3ee6be16bf31bf7b,0x3e603f3e3f7e3f62,0x3f773f713f130000,0xbf6abf043d973f22,0xbf42be793eb83f55,0x3e2fbedbbf5fbf7f,0xbf4abf80bf58bec4,0x3f803f4e3ea1be95,
0x3f653f7d3f393e48,0xbf7abf2cbdfb3ef1,0xbe893eac3f513f80,0xbecfbf5cbf7fbf46,0xbf27bf78bf6fbf0e,0x3f7c3f673efcbdc9,0x3f1d3d49bf09bf6d,0x3cc93f183f733f75,
0xbf67bef13e163f35,0x3f04bdc9bf2cbf7b,0x3d493f223f783f6d,0xbf18bf75bf71bf0e,0x3eacbe95bf4ebf80,0x3e793f463f803f55,0xbf3ebf7fbf5cbec4,0x3f7d3f623edbbe48,
0xbedbbf62bf7dbf35,0x3f5c3f7f3f3e3e48,0xbf80bf46be793ec4,0x3f4e3e95beacbf55,0x3f713f753f188000,0xbf78bf22bd493f0e,0x3f2c3dc9bf04bf6d,0xbe163ef13f673f7b,
0x3f513f803f423e48,0xbf7ebf5cbeb83e95,0xbcc93f183f773f6d,0xbee6bf67bf7abf22,0xbf58beac3ea13f55,0x3efcbe16bf39bf7f,0xbf6abf78bf1d0000,0x3f7f3f3e3e2fbef1,
0xbf133d493f273f7b,0x3dfbbf04bf6fbf75,0xbf80bf4ebe893ec4,0x3f653edbbe60bf46,0xbf09bf71bf73bf0e,0x3f5f3f7d3f313dc9,0x3ecfbe79bf4abf80,0x3d973f2c3f7c3f62,
0xbef13e483f463f80,0x3dc9bf0ebf75bf6d,0x3e953f553f7f3f35,0xbf22bf7bbf62bec4,0x3f623f7b3f220000,0xbf7fbf55be953ec4,0x3f753f0ebdc9bf35,0xbf46be483ef13f6d,
0xbf62bf7bbf228000,0x3f7f3f553e95bec4,0xbf75bf0e3dc93f35,0x3f463e48bef1bf6d,0xbef13e483f463f80,0x3dc9bf0ebf75bf6d,0x3e953f553f7f3f35,0xbf22bf7bbf62bec4,
0x3f803f3e3dfbbf0e,0xbf73bf043e2f3f46,0x3f583f7d3f270000,0xbf77bf67becf3e95,0x3eb8beacbf5fbf7b,0xbd973f183f7a3f62,0x3f513e79bee6bf6d,0xbf1d3d493f313f7f,
0x3cc93f2c3f7e3f55,0xbea1bf5cbf7cbf22,0xbf093e163f423f80,0x3e89bedbbf6abf75,0x3f6f3f713efcbe48,0xbf7fbf4ebe603ef1,0x3f133f783f653ec4,0xbf4abf80bf39bdc9,
0xbe16bf46bf80bf35,0x3eac3f623f783f0e,0xbf04bf75bf67bec4,0x3f2c3f7f3f4e3e48,0x3f18bdc9bf3ebf80,0xbedb3e953f5c3f7b,0x3e79bef1bf71bf6d,0xbd493f223f7d3f55,
0x3f7d3f22bd49bf35,0xbf71bef13e793f55,0x3f5c3e95bedbbf6d,0xbf3ebdc93f183f7b,0x3f4e3f7f3f2c8000,0xbf67bf75bf043e48,0x3f783f623eacbec4,0xbf80bf46be163f0e,
0xbf7ebf4ebe2f3f0e,0x3f803f3e3d97bf22,0xbf73bf67beb83ec4,0x3f7a3f5c3e89bef1,0xbf5fbf78bf093e48,0x3f6a3f713ee6be95,0xbf42bf80bf310000,0x3f513f7d3f1dbdc9,
0x3dfbbf18bf7cbf55,0xbcc93f2c3f7f3f46,0x3ea1bedbbf6fbf6d,0xbe603f043f773f62,0x3efcbe79bf58bf7b,0xbecf3eac3f653f75,0x3f27bd49bf39bf80,0xbf133e163f4a3f7f,
0x3f003f003f003f00,0x3f003f003f003f00,0x3f003f003f003f00,0x3f003f003f003f00,0x3f003f003f003f00,0x3f003f003f003f00,0x3f003f003f003f00,0x3f003f003f003f00,
0xbf003f00bf003f00,0xbf003f00bf003f00,0xbf003f00bf003f00,0xbf003f00bf003f00,0xbf003f00bf003f00,0xbf003f00bf003f00,0xbf003f00bf003f00,0xbf003f00bf003f00,
0x3f5f3f5c3f583f55,0x3f6a3f673f653f62,0x3f423f3e3f393f35,0x3f513f4e3f4a3f46,0x3f7e3f7d3f7c3f7b,0x3f803f803f7f3f7f,0x3f733f713f6f3f6d,0x3f7a3f783f773f75,
0x3efc3f043f093f0e,0x3ecf3edb3ee63ef1,0x3f273f2c3f313f35,0x3f133f183f1d3f22,0x3dfb3e163e2f3e48,0x3cc93d493d973dc9,0x3ea13eac3eb83ec4,0x3e603e793e893e95,
0x3f4e3f463f3e3f35,0x3f673f623f5c3f55,0x3f783f753f713f6d,0x3f803f7f3f7d3f7b,0x3e163dc93d490000,0x3eac3e953e793e48,0x3f043ef13edb3ec4,0x3f2c3f223f183f0e,
0x3f183f223f2c3f35,0x3edb3ef13f043f0e,0x3e793e953eac3ec4,0x3d493dc93e163e48,0x3f7d3f7f3f803f80,0x3f713f753f783f7b,0x3f5c3f623f673f6d,0x3f3e3f463f4e3f55,
0x3f6f3f673f5f3f55,0x3f7f3f7d3f7a3f75,0x3f133f043ee63ec4,0x3f4a3f3e3f313f22,0x3cc9bd49bdfbbe48,0x3ea13e793e2f3dc9,0xbf09bf18bf27bf35,0xbe89beacbecfbef1,
0x3eb83edb3efc3f0e,0x3d973e163e603e95,0x3f513f5c3f653f6d,0x3f1d3f2c3f393f46,0x3f803f803f7e3f7b,0x3f733f783f7c3f7f,0x3f583f4e3f423f35,0x3f773f713f6a3f62,
0xbf75bf7bbf7fbf80,0xbf46bf55bf62bf6d,0xbef1bf0ebf22bf35,0xbdc9be48be95bec4,0x3e953e483dc90000,0x3f223f0e3ef13ec4,0x3f623f553f463f35,0x3f7f3f7b3f753f6d,
0x3e953e483dc98000,0x3f223f0e3ef13ec4,0x3f623f553f463f35,0x3f7f3f7b3f753f6d,0x3f753f7b3f7f3f80,0x3f463f553f623f6d,0x3ef13f0e3f223f35,0x3dc93e483e953ec4,
0xbf58bf67bf73bf7b,0xbefcbf18bf31bf46,0xbf6abf5cbf4abf35,0xbf7fbf80bf7cbf75,0x3f513f3e3f273f0e,0x3f7e3f783f6f3f62,0xbcc9be16be89bec4,0x3ee63eac3e603dc9,
0x3f093edb3ea13e48,0x3f5f3f4e3f393f22,0xbecfbf04bf1dbf35,0x3d97bd49be2fbe95,0x3f133f2c3f423f55,0x3dfb3e793eb83ef1,0x3f803f7d3f773f6d,0x3f653f713f7a3f7f,
0xbeacbef1bf18bf35,0x3e793dc9bd49be48,0x3f3e3f223f043ec4,0x3f7d3f753f673f55,0xbedbbe95be160000,0xbf5cbf46bf2cbf0e,0xbf80bf7fbf78bf6d,0xbf4ebf62bf71bf7b,
0x3f713f623f4e3f35,0x3f783f7f3f803f7b,0x3f2c3f463f5c3f6d,0x3e163e953edb3f0e,0xbf67bf75bf7dbf80,0xbf04bf22bf3ebf55,0x3d49bdc9be79bec4,0x3f183ef13eac3e48,
0x3f273f043eb83e48,0x3f7c3f713f5f3f46,0xbf1dbf3ebf58bf6d,0x3cc9be16bea1bef1,0xbf65bf4ebf31bf0e,0xbf7abf80bf7ebf75,0x3e893edb3f133f35,0xbecfbe79bd973dc9,
0x3f423f5c3f6f3f7b,0x3e2f3eac3efc3f22,0x3f4a3f2c3f093ec4,0x3f803f7d3f733f62,0xbee6bf18bf39bf55,0x3e603d49bdfbbe95,0xbf77bf67bf51bf35,0xbf6abf78bf7fbf7f,
0x3f553f6d3f7b3f80,0x3e483ec43f0e3f35,0xbf0ebec4be480000,0xbf7bbf6dbf55bf35,0xbf55bf6dbf7bbf80,0xbe48bec4bf0ebf35,0x3f0e3ec43e480000,0x3f7b3f6d3f553f35,
0xbf0ebec4be488000,0xbf7bbf6dbf55bf35,0xbf55bf6dbf7bbf80,0xbe48bec4bf0ebf35,0x3f0e3ec43e488000,0x3f7b3f6d3f553f35,0x3f553f6d3f7b3f80,0x3e483ec43f0e3f35,
0xbd973e163eb83f0e,0xbf51bf2cbefcbe95,0x3f7e3f713f583f35,0x3f393f5c3f733f7f,0x3ee63e793cc9be48,0x3f7a3f673f4a3f22,0xbf77bf80bf7cbf6d,0xbecfbf18bf42bf62,
0xbf7fbf7dbf6fbf55,0xbf13bf3ebf5fbf75,0x3dfb3eac3f093f35,0xbf31bf04bea1bdc9,0x3f653f783f803f7b,0x3e603edb3f1d3f46,0x3e893d49be2fbec4,0x3f6a3f4e3f273ef1,
0xbf80bf75bf5cbf35,0xbf18bf46bf67bf7b,0x3eac3dc9be16bec4,0x3f783f623f3e3f0e,0x3f2c3ef13e790000,0x3f7d3f7f3f713f55,0x3edb3f223f4e3f6d,0xbf04be95bd493e48,
0xbd49be95bf04bf35,0x3f4e3f223edb3e48,0x3f713f7f3f7d3f6d,0x3e793ef13f2c3f55,0x3f3e3f623f783f80,0xbe163dc93eac3f0e,0xbf67bf46bf18bec4,0xbf5cbf75bf80bf7b,
0x3e60bd49bea1bf0e,0x3f773f5c3f313ef1,0xbf6fbf4ebf1dbec4,0xbf42bf67bf7cbf7f,0x3f513f713f7f3f7b,0xbdfb3e163ecf3f22,0x3cc9be79befcbf35,0x3f653f3e3f093e95,
0x3f7a3f803f733f55,0x3e893f043f393f62,0xbeb8bf18bf4abf6d,0x3f273edb3e2fbdc9,0xbf13beacbd973e48,0xbf7ebf7dbf6abf46,0x3f803f783f5f3f35,0x3ee63f2c3f583f75,
0xbf22bf55bf75bf80,0x3ef13e48bdc9bec4,0x3f7f3f7b3f623f35,0x3e953f0e3f463f6d,0xbf46bf0ebe950000,0xbf62bf7bbf7fbf6d,0x3dc9be48bef1bf35,0x3f753f553f223ec4,
0x3f463f0e3e958000,0x3f623f7b3f7f3f6d,0xbdc93e483ef13f35,0xbf75bf55bf22bec4,0xbf22bf55bf75bf80,0x3ef13e48bdc9bec4,0x3f7f3f7b3f623f35,0x3e953f0e3f463f6d,
0x3f6a3f3e3efc3e48,0x3f273f5c3f7a3f7f,0xbf7cbf7dbf65bf35,0xbdfbbedbbf31bf62,0xbcc9beacbf1dbf55,0x3f733f4e3f133e95,0xbf09be793d973ec4,0xbf77bf80bf6fbf46,
0x3ecf3f2c3f5f3f7b,0xbf42bf04be603dc9,0x3e2fbe16bee6bf35,0x3f7e3f673f393ef1,0x3f803f713f4a3f0e,0x3ea13f183f513f75,0xbf58bf78bf7fbf6d,0x3e89bd49beb8bf22,
0xbe793dc93edb3f35,0xbf80bf75bf4ebf0e,0xbe16bef1bf3ebf6d,0x3f713f463f043e48,0xbf5cbf22beac0000,0xbf2cbf62bf7dbf7b,0x3f183e95bd49bec4,0x3f673f7f3f783f55,
0xbf78bf7fbf67bf35,0x3d49be95bf18bf55,0x3f7d3f623f2c3ec4,0x3eac3f223f5c3f7b,0xbf04bf46bf71bf80,0x3f3e3ef13e16be48,0x3f4e3f753f803f6d,0xbedbbdc93e793f0e,
0xbe89bf18bf58bf7b,0x3f6f3f3e3ee63dc9,0x3d973edb3f393f6d,0xbf7cbf5cbf1dbe95,0x3dfbbe79bf13bf55,0x3f803f713f423ef1,0xbea13d493ecf3f35,0xbf7abf7dbf5fbf22,
0x3f773f4e3f093e48,0x3eb83f2c3f653f7f,0xbf7fbf67bf31bec4,0xbe2fbf04bf4abf75,0x3f7e3f783f513f0e,0xbcc93eac3f273f62,0xbf73bf80bf6abf35,0x3e60be16befcbf46,
0x3ec43f353f6d3f80,0xbf6dbf35bec40000,0xbec4bf35bf6dbf80,0x3f6d3f353ec40000,0x3ec43f353f6d3f80,0xbf6dbf35bec40000,0xbec4bf35bf6dbf80,0x3f6d3f353ec40000,
0xbf6dbf35bec48000,0xbec4bf35bf6dbf80,0x3f6d3f353ec48000,0x3ec43f353f6d3f80,0xbf6dbf35bec48000,0xbec4bf35bf6dbf80,0x3f6d3f353ec48000,0x3ec43f353f6d3f80,
0xbf4abf78bf7cbf55,0x3f313eacbd97bef1,0x3f653f803f6f3f35,0xbf09be163e893f22,0xbefcbf4ebf7abf7b,0x3f6a3f2c3ea1bdc9,0x3f273f673f803f6d,0xbf51bf04bdfb3e95,
0x3f1d3e79be2fbf0e,0x3f393f713f7f3f62,0xbee6bd493eb83f35,0xbf58bf7dbf77bf46,0x3f5f3f183e60be48,0x3ecf3f3e3f733f7f,0xbf42bedbbcc93ec4,0xbf13bf5cbf7ebf75,
0x3f5c3f7f3f713f35,0xbf2cbe953e163f0e,0xbf18bf62bf80bf6d,0x3f673f223e79be48,0x3f783f463edb0000,0x3d493ef13f4e3f7b,0xbf7dbf75bf3ebec4,0x3eacbdc9bf04bf55,
0xbf04bdc93eac3f35,0xbf3ebf75bf7dbf55,0x3f4e3ef13d49bec4,0x3edb3f463f783f7b,0x3e793f223f673f80,0xbf80bf62bf18be48,0x3e16be95bf2cbf6d,0x3f713f7f3f5c3f0e,
0xbf31bf71bf7ebf55,0x3f653f183e2fbe95,0x3f7a3f783f423ec4,0xbefcbd493ecf3f46,0xbf6fbf2cbe893e48,0xbd97bf04bf58bf7f,0x3f133e16bea1bf35,0x3f1d3f673f803f62,
0x3f393eacbdfbbf0e,0x3ee63f4e3f7c3f75,0xbe603e793f273f6d,0xbf5fbf80bf6abf22,0xbeb8bf3ebf77bf7b,0x3f7f3f5c3f093dc9,0x3f513f7d3f733f35,0xbf4abedb3cc93ef1,
0xbdc9bf0ebf62bf80,0x3f753f7b3f463ec4,0xbf22be483e953f35,0xbef1bf55bf7fbf6d,0x3f7f3f553ef10000,0xbe953e483f223f6d,0xbf46bf7bbf75bf35,0x3f623f0e3dc9bec4,
0x3f7f3f553ef18000,0xbe953e483f223f6d,0xbf46bf7bbf75bf35,0x3f623f0e3dc9bec4,0x3dc93f0e3f623f80,0xbf75bf7bbf46bec4,0x3f223e48be95bf35,0x3ef13f553f7f3f6d,
0xbe2f3eac3f423f7b,0xbf4abf7dbf6fbf22,0xbf39bf78bf77bf35,0x3f733f2c3e60be95,0xbf58bf80bf65bf0e,0x3f5f3f043cc9bef1,0x3f6a3f183dfbbec4,0xbd973edb3f513f7f,
0xbf7cbf71bf27be48,0x3f1d3e16beb8bf46,0x3f313e79be89bf35,0x3ea13f3e3f7a3f75,0x3f093d49bee6bf55,0x3efc3f5c3f803f62,0x3ecf3f4e3f7e3f6d,0xbf7fbf67bf13bdc9,
0x3f3e3e95be79bf35,0x3e163f223f713f7b,0xbf67bf7fbf4ebec4,0x3f5c3ef1bd49bf0e,0xbf80bf62bf040000,0x3f183dc9bedbbf55,0x3eac3f463f7d3f6d,0xbf78bf75bf2cbe48,
0x3f2c3f753f783f35,0xbf7dbf46beac3e48,0x3edbbdc9bf18bf6d,0x3f043f623f803f55,0x3d49bef1bf5cbf80,0x3f4e3f7f3f673f0e,0xbf71bf22be163ec4,0x3e79be95bf3ebf7b,
0xbf73bf78bf31be48,0x3f583edbbdfbbf22,0x3efcbd49bf13bf6d,0x3eb83f4e3f7f3f62,0x3f423f7d3f6a3f0e,0xbf7cbf3ebe893e95,0xbf4abeac3e603f35,0x3cc9bf04bf65bf7f,
0x3ea1be79bf39bf7b,0x3f093f673f7e3f46,0x3f5f3f803f513ec4,0xbf6fbf18bd973ef1,0xbf27be163ecf3f55,0xbe2fbf2cbf77bf75,0xbf1dbf71bf7abf35,0x3f803f5c3ee6bdc9,
0xbe483ec43f553f80,0xbf0ebf6dbf7bbf35,0x3f7b3f6d3f0e0000,0xbf55bec43e483f35,0x3e48bec4bf55bf80,0x3f0e3f6d3f7b3f35,0xbf7bbf6dbf0e0000,0x3f553ec4be48bf35,
0xbf7bbf6dbf0e8000,0x3f553ec4be48bf35,0xbe483ec43f553f80,0xbf0ebf6dbf7bbf35,0x3f7b3f6d3f0e8000,0xbf55bec43e483f35,0x3e48bec4bf55bf80,0x3f0e3f6d3f7b3f35,
0x3f733f183cc9bf0e,0xbf093d493f1d3f75,0x3efc3f673f7c3f35,0xbf6fbf78bf27bdc9,0xbf7fbf5cbecf3e48,0x3f513eacbe89bf46,0xbdfbbf2cbf7abf6d,0x3f393f7d3f653ef1,
0x3ea13f4e3f803f55,0xbf58bf80bf4abe95,0xbf5fbedb3e2f3f35,0x3eb8be79bf42bf7f,0x3d97bf04bf6abf7b,0x3f133f713f773f22,0x3f7e3f3e3e60bec4,0xbf31be163ee63f62,
0xbedbbf62bf7dbf35,0x3f5c3f7f3f3e3e48,0xbf80bf46be793ec4,0x3f4e3e95beacbf55,0x3f713f753f180000,0xbf78bf22bd493f0e,0x3f2c3dc9bf04bf6d,0xbe163ef13f673f7b,
0x3f673ef1be16bf35,0xbf043dc93f2c3f7b,0xbd49bf22bf78bf6d,0x3f183f753f713f0e,0xbeac3e953f4e3f80,0xbe79bf46bf80bf55,0x3f3e3f7f3f5c3ec4,0xbf7dbf62bedb3e48,
0xbf7cbf2cbd973f0e,0x3f4a3e79becfbf62,0xbf31bf7dbf5fbec4,0x3f733f713f09bdc9,0x3e60bedbbf65bf7b,0x3e893f4e3f803f46,0x3f6f3f04bdfbbf35,0xbf27bd493f133f75,
0xbe2fbf3ebf7fbf55,0x3f1d3f783f6a3ef1,0x3f393e16befcbf6d,0xbea13eac3f583f7f,0x3f7a3f673ee6be48,0xbf77bf183cc93f22,0x3eb83f5c3f7e3f35,0xbf42bf80bf51be95,
0x3ef1be48bf46bf80,0xbdc93f0e3f753f6d,0xbe95bf55bf7fbf35,0x3f223f7b3f623ec4,0xbf62bf7bbf220000,0x3f7f3f553e95bec4,0xbf75bf0e3dc93f35,0x3f463e48bef1bf6d,
0x3f623f7b3f228000,0xbf7fbf55be953ec4,0x3f753f0ebdc9bf35,0xbf46be483ef13f6d,0x3ef1be48bf46bf80,0xbdc93f0e3f753f6d,0xbe95bf55bf7fbf35,0x3f223f7b3f623ec4,
0xbf39bf80bf4abe48,0x3f653f783f13bdc9,0xbe60bf4ebf7fbf35,0x3efc3f713f6f3ef1,0xbf6abedb3e893f55,0x3f423e16bf09bf75,0xbf7cbf5cbea13ec4,0x3f7e3f2c3cc9bf22,
0x3f313d49bf1dbf7b,0xbee63e793f513f7f,0x3f7a3f18bd97bf35,0xbf5fbeac3eb83f62,0xbecfbf67bf77bf0e,0x3f273f7d3f583e95,0x3e2fbf04bf73bf6d,0x3dfb3f3e3f803f46,
0xbf7dbf223d493f35,0x3f713ef1be79bf55,0xbf5cbe953edb3f6d,0x3f3e3dc9bf18bf7b,0xbf4ebf7fbf2c0000,0x3f673f753f04be48,0xbf78bf62beac3ec4,0x3f803f463e16bf0e,
0xbe16bf46bf80bf35,0x3eac3f623f783f0e,0xbf04bf75bf67bec4,0x3f2c3f7f3f4e3e48,0x3f18bdc9bf3ebf80,0xbedb3e953f5c3f7b,0x3e79bef1bf71bf6d,0xbd493f223f7d3f55,
0xbf4abe163f133f7b,0x3f393d49bf27bf7f,0xbf65beac3ecf3f6d,0x3f583e79befcbf75,0xbf77bf043e603f55,0x3f6f3edbbea1bf62,0xbf7fbf2c3cc93f35,0x3f7c3f18bdfbbf46,
0xbf1dbf7dbf51be48,0x3f313f803f423dc9,0xbee6bf71bf6abec4,0x3f093f783f5f3e95,0xbe89bf5cbf7abf0e,0x3eb83f673f733ef1,0xbd97bf3ebf80bf35,0x3e2f3f4e3f7e3f22,
0xbf8000003f80,0xbf8000003f80,0xbf8000003f80,0xbf8000003f80,0xbf8000003f80,0xbf8000003f80,0xbf8000003f80,0xbf8000003f80,
0x3f808000bf808000,0x3f808000bf808000,0x3f808000bf808000,0x3f808000bf808000,0x3f808000bf808000,0x3f808000bf808000,0x3f808000bf808000,0x3f808000bf808000,
0xbf77be793f7a3e48,0xbf6fbeac3f733e95,0xbf7fbd493f800000,0xbf7cbe163f7e3dc9,0xbf4abf183f513f0e,0xbf39bf2c3f423f22,0xbf65bedb3f6a3ec4,0xbf58bf043f5f3ef1,
0x3e89bf78be603f7b,0x3eb8bf71bea13f75,0x3d97bf80bcc93f80,0x3e2fbf7dbdfb3f7f,0x3f1dbf4ebf133f55,0x3f31bf3ebf273f46,0x3ee6bf67becf3f6d,0x3f09bf5cbefc3f62,
0xbf4e3f223f3ebf35,0xbf673ef13f5cbf0e,0xbf783e953f71bec4,0xbf803dc93f7dbe48,0xbe163f7f3d49bf80,0xbeac3f753e79bf7b,0xbf043f623edbbf6d,0xbf2c3f463f18bf55,
0xbf18bf463f2c3f35,0xbedbbf623f043f55,0xbe79bf753eac3f6d,0xbd49bf7f3e163f7b,0xbf7dbdc93f808000,0xbf71be953f783e48,0xbf5cbef13f673ec4,0xbf3ebf223f4e3f0e,
0xbecf3f713e89bf7b,0xbf273f4e3f09bf62,0x3e2f3f78bea1bf6d,0xbdfb3f80bcc9bf7f,0x3f313f2cbf4abf0e,0x3ee63f5cbf13bf46,0x3f7a3e16bf7f0000,0x3f5f3edbbf6fbe95,
0xbf6abeac3f773e48,0xbf42bf183f583ef1,0xbf7c3e793f73bec4,0xbf7ebd493f80bdc9,0xbf393f3e3f1dbf55,0xbf653f043f51bf22,0xbe603f7d3d97bf80,0xbefc3f673eb8bf75,
0x3e95bf7bbdc93f80,0x3f22bf55bef13f6d,0x3f62bf0ebf463f35,0x3f7fbe48bf753ec4,0x3f753e48bf7f0000,0x3f463f0ebf62bec4,0x3ef13f55bf22bf35,0x3dc93f7bbe95bf6d,
0x3f753e48bf7f8000,0x3f463f0ebf62bec4,0x3ef13f55bf22bf35,0x3dc93f7bbe95bf6d,0xbe953f7b3dc9bf80,0xbf223f553ef1bf6d,0xbf623f0e3f46bf35,0xbf7f3e483f75bec4,
0xbe60bf713ee63f55,0x3e89bf7dbcc93f7f,0xbf6fbe793f7e0000,0xbf27bf2c3f513ef1,0x3f7c3d49bf7f3e48,0x3f4a3f04bf6abe95,0x3f31bf4ebefc3f6d,0x3f73bedbbf583f22,
0x3f7abeacbf653f0e,0x3f773e16bf803dc9,0x3eb8bf78bdfb3f80,0x3f42bf3ebf133f62,0xbe2f3f80bd97bf7b,0xbf1d3f5c3ecfbf75,0x3f393f18bf5fbec4,0x3ea13f67bf09bf46,
0xbeacbf623f183f35,0x3e79bf7f3d493f7b,0x3f3ebf46bf043f6d,0x3f7dbe95bf673f0e,0xbedb3f753e16bf80,0xbf5c3f223f2cbf55,0xbf803dc93f78bec4,0xbf4ebef13f713e48,
0x3f71bef1bf4e3f35,0x3f783dc9bf803e48,0x3f2c3f22bf5cbec4,0x3e163f75bedbbf55,0xbf67be953f7d8000,0xbf04bf463f3e3f0e,0x3d49bf7f3e793f6d,0x3f18bf62beac3f7b,
0xbd97bf783ecf3f55,0x3f13bf67be893f7f,0xbf7e3d493f7abec4,0xbf31bf183f653e95,0xbea13f7dbcc9bf7b,0xbf583f2c3f1dbf62,0x3f5f3eacbf7c0000,0x3eb83f5cbf27bf22,
0x3f7fbe79bf6a3f0e,0x3f513edbbf77bdc9,0x3dfbbf803e603f6d,0x3f39bf4ebee63f75,0xbf73be163f80be48,0xbf09bf3e3f4a3ef1,0xbefc3f713e2fbf80,0xbf6f3f043f42bf46,
0x3f0ebf6dbe483f80,0x3f7bbec4bf553f35,0x3f553ec4bf7b0000,0x3e483f6dbf0ebf35,0xbf0e3f6d3e48bf80,0xbf7b3ec43f55bf35,0xbf55bec43f7b0000,0xbe48bf6d3f0e3f35,
0x3f553ec4bf7b8000,0x3e483f6dbf0ebf35,0xbf0e3f6d3e48bf80,0xbf7b3ec43f55bf35,0xbf55bec43f7b8000,0xbe48bf6d3f0e3f35,0x3f0ebf6dbe483f80,0x3f7bbec4bf553f35,
0x3f42bf4ebecf3f7b,0x3f7cbd49bf773ef1,0xbf4abedb3f7a0000,0xbcc9bf783ee63f46,0xbf733f043f39bf55,0xbf58beac3f7ebdc9,0x3efc3f3ebf51bec4,0xbeb83f7dbd97bf75,
0x3f273f18bf6abe48,0xbe2f3f80be89bf62,0x3f1dbf67be603f80,0x3f80be79bf653f22,0xbea1bf5c3f313f0e,0x3f09bf71bdfb3f7f,0xbf5f3f2c3f13bf6d,0xbf6fbe163f7fbe95,
0x3f80be95bf5c3f35,0x3f183f22bf67be48,0xbeac3f7fbe16bf6d,0xbf783ef13f3ebf55,0xbf2c3f623e79bf80,0xbf7d3dc93f71bf0e,0xbedbbf463f4e3ec4,0x3f04bf75bd493f7b,
0x3d493f75bf04bf35,0xbf4e3f463edbbf7b,0xbf71bdc93f7dbec4,0xbe79bf623f2c3f0e,0xbf3ebef13f788000,0x3e16bf7f3eac3f55,0x3f67bf22bf183f6d,0x3f5c3e95bf803e48,
0x3f093f2cbf65be48,0xbefc3f78bcc9bf75,0x3ecfbf7d3dfb3f6d,0x3f7fbeacbf513f46,0xbf7c3edb3f42bf55,0xbf1dbf183f6f3dc9,0x3f313f04bf770000,0xbea13f80be60bf62,
0xbf583f3e3ee6bf7b,0xbf5fbe793f80be95,0x3f6a3e16bf7e3ec4,0x3d973f71bf13bf22,0xbe2fbf673f273f0e,0x3f4abf4ebeb83f7f,0xbf393f5c3e89bf80,0xbf73bd493f7abef1,
0x3f46bf55be953f80,0x3f623e48bf7f3ec4,0xbdc93f7bbef1bf35,0xbf753f0e3f22bf6d,0xbf22bf0e3f750000,0x3ef1bf7b3dc93f6d,0x3f7fbe48bf623f35,0x3e953f55bf46bec4,
0x3f223f0ebf758000,0xbef13f7bbdc9bf6d,0xbf7f3e483f62bf35,0xbe95bf553f463ec4,0x3f46bf55be953f80,0x3f623e48bf7f3ec4,0xbdc93f7bbef1bf35,0xbf753f0e3f22bf6d,
0x3f6f3d49bf773f0e,0xbd973f78bf09bf22,0xbf13bf183f730000,0x3f1dbf71bcc93f75,0x3f31bf67bdfb3f7b,0x3f653e16bf7c3ef1,0xbf7a3f043f27bf6d,0xbefcbf2c3f6a3dc9,
0xbeb83f80be89bf55,0xbf7f3e793f58bf46,0x3f51bf4ebea13f80,0x3f4a3eacbf803e95,0x3f393edbbf7e3e48,0xbee63f7dbe2fbf62,0xbe60bf5c3f423ec4,0x3f5fbf3ebecf3f7f,
0xbe793f7fbedbbf35,0xbf803e953f4ebf55,0xbe16bf623f3e3ec4,0x3f71bf22bf043f7b,0xbf5c3f463eacbf80,0xbf2cbef13f7dbe48,0x3f18bf753d493f6d,0x3f673dc9bf783f0e,
0xbf783dc93f67bf35,0x3d49bf753f183f0e,0x3f7dbef1bf2c3f6d,0x3eac3f46bf5cbe48,0xbf04bf223f718000,0x3f3ebf62be163f7b,0x3f4e3e95bf803ec4,0xbedb3f7fbe79bf55,
0xbf5fbe163f7abf0e,0x3ecfbf803ea13f46,0x3f423eacbf803ec4,0xbf133f78bdfbbf62,0xbf1dbf043f7cbe48,0x3f39bf67bd973f75,0x3ee63f2cbf6f0000,0xbf583f4e3e89bf7f,
0x3efcbf7d3e603f55,0x3f6a3d49bf733f22,0xbf273f71bcc9bf6d,0xbf51be793f7ebef1,0x3f4abf5cbe2f3f7b,0x3f313edbbf7f3e95,0xbf653f3e3eb8bf80,0xbf09bf183f77bdc9,
0x3f6dbf35bec43f80,0x3ec43f35bf6d0000,0xbf6d3f353ec4bf80,0xbec4bf353f6d0000,0x3f6dbf35bec43f80,0x3ec43f35bf6d0000,0xbf6d3f353ec4bf80,0xbec4bf353f6d0000,
0x3ec43f35bf6d8000,0xbf6d3f353ec4bf80,0xbec4bf353f6d8000,0x3f6dbf35bec43f80,0x3ec43f35bf6d8000,0xbf6d3f353ec4bf80,0xbec4bf353f6d8000,0x3f6dbf35bec43f80,
0x3dfb3f5cbf51be48,0xbf803edb3f27bf75,0xbea1bf3e3f6a0000,0x3f7abf18befc3f7f,0xbe893f7dbf09bf0e,0xbf6f3d493f65bf46,0x3d97bf713f313ec4,0x3f7cbe79bf4a3f62,
0xbf7e3f043f13bf7b,0xbcc9bf673f423e95,0x3f73bf2cbecf3f80,0x3e603f4ebf5fbdc9,0xbf773e163f58bf55,0x3eb8bf803ee63f22,0x3f7fbeacbf393f6d,0xbe2f3f78bf1dbef1,
0xbf5cbdc93f71bf35,0x3f2cbf753e163f55,0x3f183ef1bf803ec4,0xbf673f463e79bf7b,0xbf783f223edbbf80,0xbd49bf623f4e3e48,0x3f7dbe95bf3e3f6d,0xbeac3f7fbf04bf0e,
0x3f04bf7f3eac3f35,0x3f3e3e95bf7d3f0e,0xbf4e3f623d49bf6d,0xbedbbf223f78be48,0xbe79bf463f678000,0x3f80bef1bf183f7b,0xbe163f75bf2cbec4,0xbf713dc93f5cbf55,
0x3f80bedbbf1d3f7b,0xbea13f7dbf13bef1,0xbf583f5c3d97bf6d,0xbe89bf3e3f6fbdc9,0x3ecfbf803efc3f0e,0x3f423e79bf7a3f22,0x3e2f3f4ebf650000,0xbf7e3eac3f31bf75,
0xbcc93f67bf4abe48,0xbf733e163f51bf62,0xbf09bf043f7fbec4,0x3f77bf2cbeb83f7f,0x3f6abd49bf5f3f55,0xbf273f78be60bf46,0xbf7c3f183ee6bf80,0x3dfbbf713f393e95,
0x3f7fbf0ebef13f80,0xbe953f7bbf22bec4,0xbf46be483f75bf35,0x3f62bf55bdc93f6d,0x3dc93f55bf620000,0xbf753e483f46bf6d,0x3f22bf7b3e953f35,0x3ef13f0ebf7f3ec4,
0x3dc93f55bf628000,0xbf753e483f46bf6d,0x3f22bf7b3e953f35,0x3ef13f0ebf7f3ec4,0xbf7f3f0e3ef1bf80,0x3e95bf7b3f223ec4,0x3f463e48bf753f35,0xbf623f553dc9bf6d,
0xbf513f67bd97bf55,0xbdfbbf4e3f6abdc9,0xbcc9bf5c3f5f0000,0x3f65bd49bf583f62,0xbe60bf3e3f73be48,0x3f77be79bf393f75,0x3f6fbe16bf4a3f6d,0xbf423f71be2fbf46,
0xbf13bedb3f7fbf0e,0x3f7ebf18becf3f7f,0x3f80bf04befc3f80,0xbee63f80bf09bef1,0x3f7abf2cbea13f7b,0xbe893f78bf31be95,0xbeb83f7dbf1dbec4,0xbf27beac3f7cbf22,
0x3f3ebf753e793f35,0x3e163f46bf713e48,0xbf673dc93f4ebf6d,0x3f5cbf623d493f55,0xbf803ef13f04bf80,0x3f18bf7f3edb3f0e,0x3eac3f22bf7d3ec4,0xbf783e953f2cbf7b,
0x3f2c3e95bf783f35,0xbf7d3f223eacbf7b,0x3edbbf7f3f183ec4,0x3f043ef1bf803f0e,0x3d49bf623f5c8000,0x3f4e3dc9bf673f55,0xbf713f463e16bf6d,0x3e79bf753f3e3e48,
0xbf653f5cbcc9bf55,0x3e60bf713f4a3dc9,0xbe89bf2c3f7cbec4,0x3f6abe16bf423f75,0x3f7fbf18beb83f7b,0xbf133f80befcbef1,0xbdfb3f67bf580000,0xbf31be793f73bf46,
0xbee6bf043f80bf0e,0x3f7abeacbf1d3f7f,0x3f77bf3ebe2f3f6d,0xbecf3f7dbf27be95,0x3d973f4ebf6f3e48,0xbf51bd493f5fbf62,0xbf7e3edb3f09bf80,0x3f39bf783ea13f22,
0x3f7bbec4bf0e3f80,0xbf553f6dbe48bf35,0x3e48bf6d3f550000,0x3f0e3ec4bf7b3f35,0xbf7b3ec43f0ebf80,0x3f55bf6d3e483f35,0xbe483f6dbf550000,0xbf0ebec43f7bbf35,
0xbe483f6dbf558000,0xbf0ebec43f7bbf35,0x3f7bbec4bf0e3f80,0xbf553f6dbe48bf35,0x3e48bf6d3f558000,0x3f0e3ec4bf7b3f35,0xbf7b3ec43f0ebf80,0x3f55bf6d3e483f35,
0xbf653e163f39bf7b,0x3f7abf3ebdfb3f62,0x3e89bf713f510000,0x3ecf3f04bf7f3f22,0x3f273e79bf6f3f55,0xbf7c3edb3efcbf7f,0xbf1d3f80bf09bec4,0xbcc9bf4e3f73be95,
0x3ee6bf7d3f313e48,0x3e603f2cbf7e3ef1,0x3f77beacbf133f80,0xbf6a3f5cbd97bf46,0xbf423f78beb8bf0e,0x3e2fbf673f5fbdc9,0xbf4abd493f58bf6d,0x3f80bf18bea13f75,
0x3edb3ef1bf7d3f35,0xbf5c3dc93f3ebf7b,0x3f80bf22be793f6d,0xbf4e3f75beacbf0e,0xbf713e953f18bf80,0x3f78bf46bd493f55,0xbf2c3f7fbf04bec4,0x3e16bf623f67be48,
0xbf673f62be16bf35,0x3f04bf7f3f2c3e48,0x3d493f46bf783ec4,0xbf18be953f71bf55,0x3eacbf753f4e8000,0x3e793f22bf803f0e,0xbf3ebdc93f5cbf6d,0x3f7dbef1bedb3f7b,
0x3f13bf803f273e48,0xbdfb3f5cbf6f3e95,0x3f80bf18be893f6d,0xbf653f67be60bf22,0x3f093eacbf733f55,0xbf5f3e163f31bf7f,0xbecf3f78bf4a0000,0xbd97bf3e3f7cbef1,
0x3f51bd49bf423f7b,0xbf7e3f043eb8bf75,0xbcc93f4ebf773ec4,0xbee6bedb3f7abf46,0xbf583f71bea1bf0e,0x3efcbf7d3f393dc9,0xbf6a3e793f1dbf80,0x3f7fbf2cbe2f3f62,
0x3f62be48bf223f80,0xbf7f3f0e3e95bf6d,0x3f75bf553dc93f35,0xbf463f7bbef1bec4,0x3ef1bf7b3f460000,0xbdc93f55bf753ec4,0xbe95bf0e3f7fbf35,0x3f223e48bf623f6d,
0xbef13f7bbf468000,0x3dc9bf553f75bec4,0x3e953f0ebf7f3f35,0xbf22be483f62bf6d,0x3f62be48bf223f80,0xbf7f3f0e3e95bf6d,0x3f75bf553dc93f35,0xbf463f7bbef1bec4,
0xbcc9bf3e3f7ebf0e,0x3ea13f04bf7c3f46,0x3f09bf7d3f420000,0xbe893f67bf6a3e95,0xbf6f3eac3efcbf7b,0x3f7fbf18be603f62,0xbf13be793f65bf6d,0x3f4abd49bf393f7f,
0x3f80bf2cbdfb3f55,0xbf733f5cbe2fbf22,0x3f58be16bf273f80,0xbf773edb3ecfbf75,0x3eb8bf713f5fbe48,0xbd973f4ebf7a3ef1,0x3f51bf783ee63ec4,0xbf1d3f80bf31bdc9,
0xbf7d3f46bd49bf35,0x3f71bf623e793f0e,0xbf5c3f75bedbbec4,0x3f3ebf7f3f183e48,0xbf4e3dc93f2cbf80,0x3f67be95bf043f7b,0xbf783ef13eacbf6d,0x3f80bf22be163f55,
0xbe16bf223f80bf35,0x3eac3ef1bf783f55,0xbf04be953f67bf6d,0x3f2c3dc9bf4e3f7b,0x3f18bf7f3f3e8000,0xbedb3f75bf5c3e48,0x3e79bf623f71bec4,0xbd493f46bf7d3f0e,
0xbdfb3f4ebf7c3f0e,0x3cc9bf3e3f7fbf22,0xbea13f67bf6f3ec4,0x3e60bf5c3f77bef1,0xbefc3f78bf583e48,0x3ecfbf713f65be95,0xbf273f80bf390000,0x3f13bf7d3f4abdc9,
0xbf7e3f183e2fbf55,0x3f80bf2cbd973f46,0xbf733edb3eb8bf6d,0x3f7abf04be893f62,0xbf5f3e793f09bf7b,0x3f6abeacbee63f75,0xbf423d493f31bf80,0x3f51be16bf1d3f7f,
0xbf8000003f80,0xbf8000003f80,0xbf8000003f80,0xbf8000003f80,0xbf8000003f80,0xbf8000003f80,0xbf8000003f80,0xbf8000003f80,
0x3f808000bf808000,0x3f808000bf808000,0x3f808000bf808000,0x3f808000bf808000,0x3f808000bf808000,0x3f808000bf808000,0x3f808000bf808000,0x3f808000bf808000,
0xbefcbf5c3f093f55,0xbecfbf673ee63f62,0xbf27bf3e3f313f35,0xbf13bf4e3f1d3f46,0xbdfbbf7d3e2f3f7b,0xbcc9bf803d973f7f,0xbea1bf713eb83f6d,0xbe60bf783e893f75,
0x3f5fbf04bf583f0e,0x3f6abedbbf653ef1,0x3f42bf2cbf393f35,0x3f51bf18bf4a3f22,0x3f7ebe16bf7c3e48,0x3f80bd49bf7f3dc9,0x3f73beacbf6f3ec4,0x3f7abe79bf773e95,
0xbf18bf463f2c3f35,0xbedbbf623f043f55,0xbe79bf753eac3f6d,0xbd49bf7f3e163f7b,0xbf7dbdc93f800000,0xbf71be953f783e48,0xbf5cbef13f673ec4,0xbf3ebf223f4e3f0e,
0x3f4ebf22bf3e3f35,0x3f67bef1bf5c3f0e,0x3f78be95bf713ec4,0x3f80bdc9bf7d3e48,0x3e16bf7fbd493f80,0x3eacbf75be793f7b,0x3f04bf62bedb3f6d,0x3f2cbf46bf183f55,
0xbeb8bf673efc3f55,0xbd97bf7d3e603f75,0xbf51bf043f653ec4,0xbf1dbf3e3f393f22,0xbf803d493f7ebe48,0xbf73be793f7c3dc9,0xbf583f183f42bf35,0xbf773eac3f6abef1,
0x3f6fbedbbf5f3f0e,0x3f7fbe16bf7a3e95,0x3f13bf5cbee63f6d,0x3f4abf2cbf313f46,0x3cc9bf803dfb3f7b,0x3ea1bf78be2f3f7f,0xbf09bf4e3f273f35,0xbe89bf713ecf3f62,
0xbe953f7b3dc9bf80,0xbf223f553ef1bf6d,0xbf623f0e3f46bf35,0xbf7f3e483f75bec4,0xbf75be483f7f0000,0xbf46bf0e3f623ec4,0xbef1bf553f223f35,0xbdc9bf7b3e953f6d,
0xbf75be483f7f8000,0xbf46bf0e3f623ec4,0xbef1bf553f223f35,0xbdc9bf7b3e953f6d,0x3e95bf7bbdc93f80,0x3f22bf55bef13f6d,0x3f62bf0ebf463f35,0x3f7fbe48bf753ec4,
0xbf093f673ea1bf7b,0xbf5f3f183f39bf46,0x3ecf3f5cbf1dbf35,0xbd973f80be2fbf75,0xbf13bf3e3f423f0e,0xbdfbbf783eb83f62,0xbf803e163f77bec4,0xbf65beac3f7a3dc9,
0xbf58bedb3f733e48,0xbefcbf4e3f313f22,0xbf6a3f043f4abf35,0xbf7f3d493f7cbe95,0x3f51bf2cbf273f55,0x3f7ebe79bf6f3ef1,0xbcc9bf7d3e893f6d,0x3ee6bf71be603f7f,
0xbf713ef13f4ebf35,0xbf78bdc93f80be48,0xbf2cbf223f5c3ec4,0xbe16bf753edb3f55,0x3f673e95bf7d0000,0x3f043f46bf3ebf0e,0xbd493f7fbe79bf6d,0xbf183f623eacbf7b,
0xbeacbf623f183f35,0x3e79bf7f3d493f7b,0x3f3ebf46bf043f6d,0x3f7dbe95bf673f0e,0xbedb3f753e16bf80,0xbf5c3f223f2cbf55,0xbf803dc93f78bec4,0xbf4ebef13f713e48,
0xbf42bf043f6f3e48,0xbe2fbf713efc3f46,0xbf4a3f3e3f09bf6d,0xbf803e163f73bef1,0x3ee63f4ebf39bf0e,0xbe603f80bdfbbf75,0x3f77bedbbf513f35,0x3f6a3e79bf7f3dc9,
0x3f27bf5cbeb83f7b,0x3f7cbeacbf5f3f22,0xbf1dbf2c3f583ec4,0x3cc9bf7d3ea13f62,0xbf653f183f31bf55,0xbf7abd493f7ebe95,0x3e893f67bf13bf35,0xbecf3f783d97bf7f,
0x3f0ebf6dbe483f80,0x3f7bbec4bf553f35,0x3f553ec4bf7b0000,0x3e483f6dbf0ebf35,0xbf0e3f6d3e48bf80,0xbf7b3ec43f55bf35,0xbf55bec43f7b0000,0xbe48bf6d3f0e3f35,
0x3f553ec4bf7b8000,0x3e483f6dbf0ebf35,0xbf0e3f6d3e48bf80,0xbf7b3ec43f55bf35,0xbf55bec43f7b8000,0xbe48bf6d3f0e3f35,0x3f0ebf6dbe483f80,0x3f7bbec4bf553f35,
0x3f7fbe16bf6f3f0e,0x3f133f2cbf5fbe95,0xbdfbbf713f093f35,0x3f31bf5cbea13f7f,0xbf65be793f80be48,0xbe60bf673f1d3f22,0xbe893f80be2fbf6d,0xbf6a3f183f27bf62,
0xbd973f7dbeb8bf55,0xbf513f3e3efcbf75,0x3f7ebeacbf583f35,0x3f393f04bf73bdc9,0x3ee6bf78bcc93f7b,0x3f7abedbbf4a3f46,0xbf77bd493f7cbec4,0xbecfbf4e3f423ef1,
0x3d493f75bf04bf35,0xbf4e3f463edbbf7b,0xbf71bdc93f7dbec4,0xbe79bf623f2c3f0e,0xbf3ebef13f780000,0x3e16bf7f3eac3f55,0x3f67bf22bf183f6d,0x3f5c3e95bf803e48,
0xbf803e953f5cbf35,0xbf18bf223f673e48,0x3eacbf7f3e163f6d,0x3f78bef1bf3e3f55,0x3f2cbf62be793f80,0x3f7dbdc9bf713f0e,0x3edb3f46bf4ebec4,0xbf043f753d49bf7b,
0xbf7a3d493f73bf0e,0xbe89bf5c3f393ef1,0x3eb83f4ebf4abec4,0xbf273f673e2fbf7f,0x3f13bf71bd973f7b,0x3f7ebe16bf6a3f22,0xbf803e793f5fbf35,0xbee6bf3e3f583e95,
0x3e60bf803ea13f55,0x3f77bf04bf313f62,0xbf6f3f183f1dbf6d,0xbf42bedb3f7cbdc9,0x3f513eacbf7f3e48,0xbdfb3f7dbecfbf46,0x3cc9bf783efc3f35,0x3f65bf2cbf093f75,
0xbf463f553e95bf80,0xbf62be483f7fbec4,0x3dc9bf7b3ef13f35,0x3f75bf0ebf223f6d,0x3f223f0ebf750000,0xbef13f7bbdc9bf6d,0xbf7f3e483f62bf35,0xbe95bf553f463ec4,
0xbf22bf0e3f758000,0x3ef1bf7b3dc93f6d,0x3f7fbe48bf623f35,0x3e953f55bf46bec4,0xbf463f553e95bf80,0xbf62be483f7fbec4,0x3dc9bf7b3ef13f35,0x3f75bf0ebf223f6d,
0xbecfbf3e3f5f3e48,0x3f42bf5cbe603f7f,0xbe2f3f7dbee6bf35,0xbf7e3edb3f39bf62,0xbf803eac3f4abf55,0xbea1bf4e3f513e95,0x3f583e79bf7f3ec4,0xbe893f80beb8bf46,
0x3f6abf2cbefc3f7b,0x3f273f04bf7a3dc9,0xbf7c3e163f65bf35,0xbdfbbf673f313ef1,0xbcc9bf713f1d3f0e,0x3f73bf18bf133f75,0xbf093f78bd97bf6d,0xbf773d493f6fbf22,
0x3f78bdc9bf673f35,0xbd493f75bf18bf0e,0xbf7d3ef13f2cbf6d,0xbeacbf463f5c3e48,0x3f043f22bf710000,0xbf3e3f623e16bf7b,0xbf4ebe953f80bec4,0x3edbbf7f3e793f55,
0xbe793f7fbedbbf35,0xbf803e953f4ebf55,0xbe16bf623f3e3ec4,0x3f71bf22bf043f7b,0xbf5c3f463eacbf80,0xbf2cbef13f7dbe48,0x3f18bf753d493f6d,0x3f673dc9bf783f0e,
0xbf773f183f09bf7b,0xbeb8bf3e3f653dc9,0x3f7fbedbbf313f6d,0x3e2f3f5cbf4abe95,0xbf7e3e793f51bf55,0x3cc9bf713f273ef1,0x3f73bd49bf6a3f35,0xbe603f7dbefcbf22,
0xbe89bf4e3f583e48,0x3f6fbf2cbee63f7f,0x3d973f67bf39bec4,0xbf7c3f043f1dbf75,0x3dfbbf783f133f0e,0x3f80beacbf423f62,0xbea13f80becfbf35,0xbf7a3e163f5fbf46,
0x3f6dbf35bec43f80,0x3ec43f35bf6d0000,0xbf6d3f353ec4bf80,0xbec4bf353f6d0000,0x3f6dbf35bec43f80,0x3ec43f35bf6d0000,0xbf6d3f353ec4bf80,0xbec4bf353f6d0000,
0x3ec43f35bf6d8000,0xbf6d3f353ec4bf80,0xbec4bf353f6d8000,0x3f6dbf35bec43f80,0x3ec43f35bf6d8000,0xbf6d3f353ec4bf80,0xbec4bf353f6d8000,0x3f6dbf35bec43f80,
0xbf1d3f78be2fbf55,0xbf39beac3f7fbef1,0x3ee6bf803eb83f35,0x3f583e16bf773f22,0xbf5f3f4e3e60bf7b,0xbecfbf2c3f73bdc9,0x3f42bf67bcc93f6d,0x3f133f04bf7e3e95,
0xbf4abe793f7cbf0e,0x3f31bf713d973f62,0x3f653d49bf6f3f35,0xbf093f7dbe89bf46,0xbefcbf183f7abe48,0x3f6abf3ebea13f7f,0x3f273edbbf803ec4,0xbf513f5c3dfbbf75,
0x3f04bf7f3eac3f35,0x3f3e3e95bf7d3f0e,0xbf4e3f623d49bf6d,0xbedbbf223f78be48,0xbe79bf463f670000,0x3f80bef1bf183f7b,0xbe163f75bf2cbec4,0xbf713dc93f5cbf55,
0x3f5c3dc9bf713f35,0xbf2c3f75be16bf55,0xbf18bef13f80bec4,0x3f67bf46be793f7b,0x3f78bf22bedb3f80,0x3d493f62bf4ebe48,0xbf7d3e953f3ebf6d,0x3eacbf7f3f043f0e,
0xbf393f71bdfbbf55,0xbee6bf183f7cbe95,0x3e60bf783f273ec4,0x3f5f3d49bf6a3f46,0x3eb83f2cbf773e48,0xbf7f3f043f09bf7f,0xbf51be163f73bf35,0x3f4abf673cc93f62,
0xbf31beac3f7ebf0e,0x3f65bf4ebe2f3f75,0x3f7abe79bf423f6d,0xbefc3f80becfbf22,0xbf6f3f3e3e89bf7b,0xbd97bf5c3f583dc9,0x3f13bf7d3ea13f35,0x3f1d3edbbf803ef1,
0xbf7f3f0e3ef1bf80,0x3e95bf7b3f223ec4,0x3f463e48bf753f35,0xbf623f553dc9bf6d,0xbdc9bf553f620000,0x3f75be48bf463f6d,0xbf223f7bbe95bf35,0xbef1bf0e3f7fbec4,
0xbdc9bf553f628000,0x3f75be48bf463f6d,0xbf223f7bbe95bf35,0xbef1bf0e3f7fbec4,0x3f7fbf0ebef13f80,0xbe953f7bbf22bec4,0xbf46be483f75bf35,0x3f62bf55bdc93f6d,
0x3f7cbeacbf273f7b,0xbf1d3f7dbeb8bf22,0xbf313f78be89bf35,0xbea1bf2c3f7abe95,0xbf093f80bee6bf0e,0xbefcbf043f80bef1,0xbecfbf183f7ebec4,0x3f7fbedbbf133f7f,
0xbe2f3f71bf42be48,0xbf4abe163f6fbf46,0xbf39be793f77bf35,0x3f73bf3ebe603f75,0xbf58bd493f65bf55,0x3f5fbf5cbcc93f62,0x3f6abf4ebdfb3f6d,0xbd973f67bf51bdc9,
0xbf2cbe953f78bf35,0x3f7dbf22beac3f7b,0xbedb3f7fbf18bec4,0xbf04bef13f80bf0e,0xbd493f62bf5c0000,0xbf4ebdc93f67bf55,0x3f71bf46be163f6d,0xbe793f75bf3ebe48,
0x3f3ebf753e793f35,0x3e163f46bf713e48,0xbf673dc93f4ebf6d,0x3f5cbf623d493f55,0xbf803ef13f04bf80,0x3f18bf7f3edb3f0e,0x3eac3f22bf7d3ec4,0xbf783e953f2cbf7b,
0xbea13f78bf39be48,0xbf09bedb3f7ebf22,0xbf5f3d493f51bf6d,0x3f6fbf4ebd973f62,0x3f27bf7d3ecf3f0e,0x3e2f3f3ebf773e95,0x3f1d3eacbf7a3f35,0xbf803f043ee6bf7f,
0xbf733e793f31bf7b,0x3f58bf673dfb3f46,0x3efcbf803f133ec4,0x3eb83f18bf7f3ef1,0x3f423e16bf6a3f55,0xbf7c3f2c3e89bf75,0xbf4a3f71be60bf35,0x3cc9bf5c3f65bdc9,
0x3f7bbec4bf0e3f80,0xbf553f6dbe48bf35,0x3e48bf6d3f550000,0x3f0e3ec4bf7b3f35,0xbf7b3ec43f0ebf80,0x3f55bf6d3e483f35,0xbe483f6dbf550000,0xbf0ebec43f7bbf35,
0xbe483f6dbf558000,0xbf0ebec43f7bbf35,0x3f7bbec4bf0e3f80,0xbf553f6dbe48bf35,0x3e48bf6d3f558000,0x3f0e3ec4bf7b3f35,0xbf7b3ec43f0ebf80,0x3f55bf6d3e483f35,
0xbea1bf183f80bf0e,0x3f58bd49bf4a3f75,0x3f5fbf673e2f3f35,0xbeb83f78bf42bdc9,0xbd973f5cbf6a3e48,0xbf13beac3f77bf46,0xbf7e3f2c3e60bf6d,0x3f31bf7d3ee63ef1,
0x3f73bf4ebcc93f55,0xbf093f80bf1dbe95,0x3efc3edbbf7c3f35,0xbf6f3e793f27bf7f,0xbf7f3f043ecfbf7b,0x3f51bf713e893f22,0xbdfbbf3e3f7abec4,0x3f393e16bf653f62,
0xbf673f62be16bf35,0x3f04bf7f3f2c3e48,0x3d493f46bf783ec4,0xbf18be953f71bf55,0x3eacbf753f4e0000,0x3e793f22bf803f0e,0xbf3ebdc93f5cbf6d,0x3f7dbef1bedb3f7b,
0xbedbbef13f7dbf35,0x3f5cbdc9bf3e3f7b,0xbf803f223e79bf6d,0x3f4ebf753eac3f0e,0x3f71be95bf183f80,0xbf783f463d49bf55,0x3f2cbf7f3f043ec4,0xbe163f62bf673e48,
0x3e2f3f2cbf7f3f0e,0xbf1dbe793f6abf62,0xbf393f7dbefcbec4,0x3ea1bf713f58bdc9,0xbf7a3edb3ee6bf7b,0x3f77bf4e3cc93f46,0xbeb8bf043f7ebf35,0x3f423d49bf513f75,
0xbf7c3f3e3d97bf55,0x3f4abf783ecf3ef1,0xbf31be163f5fbf6d,0x3f73beacbf093f7f,0x3e60bf673f65be48,0x3e893f18bf803f22,0x3f6fbf5c3dfb3f35,0xbf273f80bf13be95,
0xbf623e483f22bf80,0x3f7fbf0ebe953f6d,0xbf753f55bdc9bf35,0x3f46bf7b3ef13ec4,0xbef13f7bbf460000,0x3dc9bf553f75bec4,0x3e953f0ebf7f3f35,0xbf22be483f62bf6d,
0x3ef1bf7b3f468000,0xbdc93f55bf753ec4,0xbe95bf0e3f7fbf35,0x3f223e48bf623f6d,0xbf623e483f22bf80,0x3f7fbf0ebe953f6d,0xbf753f55bdc9bf35,0x3f46bf7b3ef13ec4,
0xbf313f80bf1dbe48,0x3ee6bf783f51bdc9,0xbf7a3f4ebd97bf35,0x3f5fbf713eb83ef1,0x3ecf3edbbf773f55,0xbf27be163f58bf75,0xbe2f3f5cbf733ec4,0xbdfbbf2c3f80bf22,
0xbf39bd493f4abf7b,0x3f65be79bf133f7f,0xbe60bf183f7fbf35,0x3efc3eacbf6f3f62,0xbf6a3f67be89bf0e,0x3f42bf7d3f093e95,0xbf7c3f043ea1bf6d,0x3f7ebf3ebcc93f46,
0x3e163f22bf803f35,0xbeacbef13f78bf55,0x3f043e95bf673f6d,0xbf2cbdc93f4ebf7b,0xbf183f7fbf3e0000,0x3edbbf753f5cbe48,0xbe793f62bf713ec4,0x3d49bf463f7dbf0e,
0xbf7d3f46bd49bf35,0x3f71bf623e793f0e,0xbf5c3f75bedbbec4,0x3f3ebf7f3f183e48,0xbf4e3dc93f2cbf80,0x3f67be95bf043f7b,0xbf783ef13eacbf6d,0x3f80bf22be163f55,
0x3f1d3e16bf513f7b,0xbf31bd493f42bf7f,0x3ee63eacbf6a3f6d,0xbf09be793f5fbf75,0x3e893f04bf7a3f55,0xbeb8bedb3f73bf62,0x3d973f2cbf803f35,0xbe2fbf183f7ebf46,
0xbf4a3f7dbf13be48,0x3f39bf803f273dc9,0xbf653f71becfbec4,0x3f58bf783efc3e95,0xbf773f5cbe60bf0e,0x3f6fbf673ea13ef1,0xbf7f3f3ebcc9bf35,0x3f7cbf4e3dfb3f22,
0xbf3500003f353f80,0x3f350000bf35bf80,0xbf3500003f353f80,0x3f350000bf35bf80,0xbf3500003f353f80,0x3f350000bf35bf80,0xbf3500003f353f80,0x3f350000bf35bf80,
0xbf35bf80bf358000,0x3f353f803f358000,0xbf35bf80bf358000,0x3f353f803f358000,0xbf35bf80bf358000,0x3f353f803f358000,0xbf35bf80bf358000,0x3f353f803f358000,
0xbe893e79be603e48,0xbeb83eacbea13e95,0xbd973d49bcc90000,0xbe2f3e16bdfb3dc9,0xbf1d3f18bf133f0e,0xbf313f2cbf273f22,0xbee63edbbecf3ec4,0xbf093f04befc3ef1,
0xbf773f78bf7a3f7b,0xbf6f3f71bf733f75,0xbf7f3f80bf803f80,0xbf7c3f7dbf7e3f7f,0xbf4a3f4ebf513f55,0xbf393f3ebf423f46,0xbf653f67bf6a3f6d,0xbf583f5cbf5f3f62,
0x3f18bf223f2cbf35,0x3edbbef13f04bf0e,0x3e79be953eacbec4,0x3d49bdc93e16be48,0x3f7dbf7f3f80bf80,0x3f71bf753f78bf7b,0x3f5cbf623f67bf6d,0x3f3ebf463f4ebf55,
0xbf4e3f46bf3e3f35,0xbf673f62bf5c3f55,0xbf783f75bf713f6d,0xbf803f7fbf7d3f7b,0xbe163dc9bd498000,0xbeac3e95be793e48,0xbf043ef1bedb3ec4,0xbf2c3f22bf183f0e,
0x3f6abf713f77bf7b,0x3f42bf4e3f58bf62,0x3f7cbf783f73bf6d,0x3f7ebf803f80bf7f,0x3f39bf2c3f1dbf0e,0x3f65bf5c3f51bf46,0x3e60be163d970000,0x3efcbedb3eb8be95,
0xbecf3eacbe893e48,0xbf273f18bf093ef1,0x3e2fbe793ea1bec4,0xbdfb3d493cc9bdc9,0x3f31bf3e3f4abf55,0x3ee6bf043f13bf22,0x3f7abf7d3f7fbf80,0x3f5fbf673f6fbf75,
0xbf753f7bbf7f3f80,0xbf463f55bf623f6d,0xbef13f0ebf223f35,0xbdc93e48be953ec4,0x3e95be483dc90000,0x3f22bf0e3ef1bec4,0x3f62bf553f46bf35,0x3f7fbf7b3f75bf6d,
0x3e95be483dc98000,0x3f22bf0e3ef1bec4,0x3f62bf553f46bf35,0x3f7fbf7b3f75bf6d,0x3f75bf7b3f7fbf80,0x3f46bf553f62bf6d,0x3ef1bf0e3f22bf35,0x3dc9be483e95bec4,
0xbf7a3f71bf653f55,0xbf773f7dbf803f7f,0xbeb83e79bdfb0000,0xbf423f2cbf133ef1,0x3e2fbd49bd973e48,0x3f1dbf043ecfbe95,0xbf393f4ebf5f3f6d,0xbea13edbbf093f22,
0xbe603eacbee63f0e,0x3e89be163cc93dc9,0xbf6f3f78bf7e3f80,0xbf273f3ebf513f62,0x3f7cbf803f7fbf7b,0x3f4abf5c3f6abf75,0x3f31bf183efcbec4,0x3f73bf673f58bf46,
0xbf713f62bf4e3f35,0xbf783f7fbf803f7b,0xbf2c3f46bf5c3f6d,0xbe163e95bedb3f0e,0x3f67bf753f7dbf80,0x3f04bf223f3ebf55,0xbd49bdc93e79bec4,0xbf183ef1beac3e48,
0xbeac3ef1bf183f35,0x3e79bdc9bd493e48,0x3f3ebf223f04bec4,0x3f7dbf753f67bf55,0xbedb3e95be168000,0xbf5c3f46bf2c3f0e,0xbf803f7fbf783f6d,0xbf4e3f62bf713f7b,
0xbf7f3f78bf6a3f55,0xbf513f67bf773f7f,0xbdfbbd493e60bec4,0xbf393f18bee63e95,0x3f73bf7d3f80bf7b,0x3f09bf2c3f4abf62,0x3efcbeac3e2f0000,0x3f6fbf5c3f42bf22,
0xbd973e79becf3f0e,0x3f13bedb3e89bdc9,0xbf7e3f80bf7a3f6d,0xbf313f4ebf653f75,0xbea13e163cc9be48,0xbf583f3ebf1d3ef1,0x3f5fbf713f7cbf80,0x3eb8bf043f27bf46,
0xbf553f6dbf7b3f80,0xbe483ec4bf0e3f35,0x3f0ebec43e480000,0x3f7bbf6d3f55bf35,0x3f55bf6d3f7bbf80,0x3e48bec43f0ebf35,0xbf0e3ec4be480000,0xbf7b3f6dbf553f35,
0x3f0ebec43e488000,0x3f7bbf6d3f55bf35,0x3f55bf6d3f7bbf80,0x3e48bec43f0ebf35,0xbf0e3ec4be488000,0xbf7b3f6dbf553f35,0xbf553f6dbf7b3f80,0xbe483ec4bf0e3f35,
0xbf273f4ebf6a3f7b,0x3e2f3d49be893ef1,0xbf1d3edbbe600000,0xbf803f78bf653f46,0x3ea1bf043f31bf55,0xbf093eacbdfbbdc9,0x3f5fbf3e3f13bec4,0x3f6fbf7d3f7fbf75,
0x3f42bf183ecfbe48,0x3f7cbf803f77bf62,0xbf4a3f67bf7a3f80,0xbcc93e79bee63f22,0xbf733f5cbf393f0e,0xbf583f71bf7e3f7f,0x3efcbf2c3f51bf6d,0xbeb83e163d97be95,
0xbd493e95bf043f35,0x3f4ebf223edbbe48,0x3f71bf7f3f7dbf6d,0x3e79bef13f2cbf55,0x3f3ebf623f78bf80,0xbe16bdc93eacbf0e,0xbf673f46bf183ec4,0xbf5c3f75bf803f7b,
0x3f80bf753f5cbf35,0x3f18bf463f67bf7b,0xbeac3dc93e16bec4,0xbf783f62bf3e3f0e,0xbf2c3ef1be798000,0xbf7d3f7fbf713f55,0xbedb3f22bf4e3f6d,0x3f04be953d493e48,
0x3f58bf2c3ee6be48,0x3f5fbf783f80bf75,0xbf6a3f7dbf7e3f6d,0xbd973eacbf133f46,0x3e2fbedb3f27bf55,0xbf4a3f18beb83dc9,0x3f39bf043e890000,0x3f73bf803f7abf62,
0x3f09bf3e3f65bf7b,0xbefc3e793cc9be95,0x3ecfbe16bdfb3ec4,0x3f7fbf713f51bf22,0xbf7c3f67bf423f0e,0xbf1d3f4ebf6f3f7f,0x3f31bf5c3f77bf80,0xbea13d493e60bef1,
0xbf223f55bf753f80,0x3ef1be48bdc93ec4,0x3f7fbf7b3f62bf35,0x3e95bf0e3f46bf6d,0xbf463f0ebe950000,0xbf623f7bbf7f3f6d,0x3dc93e48bef13f35,0x3f75bf553f22bec4,
0x3f46bf0e3e958000,0x3f62bf7b3f7fbf6d,0xbdc9be483ef1bf35,0xbf753f55bf223ec4,0xbf223f55bf753f80,0x3ef1be48bdc93ec4,0x3f7fbf7b3f62bf35,0x3e95bf0e3f46bf6d,
0x3eb8bd49be893f0e,0x3f7fbf783f58bf22,0xbf513f18bea10000,0xbf4a3f71bf803f75,0xbf393f67bf7e3f7b,0x3ee6be16be2f3ef1,0x3e60bf043f42bf6d,0xbf5f3f2cbecf3dc9,
0x3f6fbf803f77bf55,0xbd97be793f09bf46,0xbf133f4ebf733f80,0x3f1dbeac3cc93e95,0x3f31bedb3dfb3e48,0x3f65bf7d3f7cbf62,0xbf7a3f5cbf273ec4,0xbefc3f3ebf6a3f7f,
0x3f78bf7f3f67bf35,0xbd49be953f18bf55,0xbf7d3f62bf2c3ec4,0xbeac3f22bf5c3f7b,0x3f04bf463f71bf80,0xbf3e3ef1be16be48,0xbf4e3f75bf803f6d,0x3edbbdc9be793f0e,
0xbe79bdc93edbbf35,0xbf803f75bf4e3f0e,0xbe163ef1bf3e3f6d,0x3f71bf463f04be48,0xbf5c3f22beac8000,0xbf2c3f62bf7d3f7b,0x3f18be95bd493ec4,0x3f67bf7f3f78bf55,
0xbefc3e163e60bf0e,0xbf6a3f80bf733f46,0x3f27beacbcc93ec4,0x3f51bf783f7ebf62,0xbf4a3f04be2fbe48,0xbf313f67bf7f3f75,0x3f65bf2c3eb80000,0x3f09bf4e3f77bf7f,
0xbf5f3f7dbf7a3f55,0x3ecfbd49bea13f22,0x3f42bf713f80bf6d,0xbf133e793dfbbef1,0xbf1d3f5cbf7c3f7b,0x3f39bedb3d973e95,0x3ee6bf3e3f6fbf80,0xbf583f18be89bdc9,
0xbec43f35bf6d3f80,0x3f6dbf353ec40000,0x3ec4bf353f6dbf80,0xbf6d3f35bec40000,0xbec43f35bf6d3f80,0x3f6dbf353ec40000,0x3ec4bf353f6dbf80,0xbf6d3f35bec40000,
0x3f6dbf353ec48000,0x3ec4bf353f6dbf80,0xbf6d3f35bec48000,0xbec43f35bf6d3f80,0x3f6dbf353ec48000,0x3ec4bf353f6dbf80,0xbf6d3f35bec48000,0xbec43f35bf6d3f80,
0x3f7ebf5c3f13be48,0x3cc9bedb3f42bf75,0xbf733f3ebecf0000,0xbe603f18bf5f3f7f,0x3f77bf7d3f58bf0e,0xbeb8bd493ee6bf46,0xbf7f3f71bf393ec4,0x3e2f3e79bf1d3f62,
0x3dfbbf043f51bf7b,0xbf803f67bf273e95,0xbea13f2cbf6a3f80,0x3f7abf4e3efcbdc9,0xbe89be163f09bf55,0xbf6f3f80bf653f22,0x3d973eacbf313f6d,0x3f7cbf783f4abef1,
0xbf043dc93eacbf35,0xbf3e3f75bf7d3f55,0x3f4ebef13d493ec4,0x3edbbf463f78bf7b,0x3e79bf223f67bf80,0xbf803f62bf183e48,0x3e163e95bf2c3f6d,0x3f71bf7f3f5cbf0e,
0xbf5c3f7fbf713f35,0x3f2cbe95be163f0e,0x3f18bf623f80bf6d,0xbf673f22be79be48,0xbf783f46bedb8000,0xbd493ef1bf4e3f7b,0x3f7dbf753f3ebec4,0xbeacbdc93f04bf55,
0x3cc93edbbf4a3f7b,0x3f73bf7d3f51bef1,0x3f09bf5c3f7fbf6d,0xbf773f3ebeb8bdc9,0xbf6a3f80bf5f3f0e,0x3f27be79be603f22,0x3f7cbf4e3ee60000,0xbdfbbeac3f39bf75,
0x3f80bf673f1dbe48,0xbea1be163f13bf62,0xbf583f04bd97bec4,0xbe893f2cbf6f3f7f,0x3ecf3d49befc3f55,0x3f42bf783f7abf46,0x3e2fbf183f65bf80,0xbf7e3f71bf313e95,
0xbdc93f0ebf623f80,0x3f75bf7b3f46bec4,0xbf223e483e95bf35,0xbef13f55bf7f3f6d,0x3f7fbf553ef10000,0xbe95be483f22bf6d,0xbf463f7bbf753f35,0x3f62bf0e3dc93ec4,
0x3f7fbf553ef18000,0xbe95be483f22bf6d,0xbf463f7bbf753f35,0x3f62bf0e3dc93ec4,0x3dc9bf0e3f62bf80,0xbf753f7bbf463ec4,0x3f22be48be953f35,0x3ef1bf553f7fbf6d,
0x3f13bf673f7fbf55,0xbf7e3f4ebecfbdc9,0xbf803f5cbefc0000,0x3ee63d49bf093f62,0xbf7a3f3ebea1be48,0x3e893e79bf313f75,0x3eb83e16bf1d3f6d,0x3f27bf713f7cbf46,
0xbf513edb3d97bf0e,0xbdfb3f18bf6a3f7f,0xbcc93f04bf5f3f80,0x3f65bf803f58bef1,0xbe603f2cbf733f7b,0x3f77bf783f39be95,0x3f6fbf7d3f4abec4,0xbf423eac3e2fbf22,
0xbf2c3f75bf783f35,0x3f7dbf463eac3e48,0xbedbbdc93f18bf6d,0xbf043f62bf803f55,0xbd49bef13f5cbf80,0xbf4e3f7fbf673f0e,0x3f71bf223e163ec4,0xbe79be953f3ebf7b,
0x3f3ebe95be793f35,0x3e16bf223f71bf7b,0xbf673f7fbf4e3ec4,0x3f5cbef1bd493f0e,0xbf803f62bf048000,0x3f18bdc9bedb3f55,0x3eacbf463f7dbf6d,0xbf783f75bf2c3e48,
0x3ee6bf5c3f80bf55,0xbf7a3f71bf1d3dc9,0xbf773f2cbe2fbec4,0x3ecf3e16bf273f75,0xbd973f18bf6f3f7b,0x3f51bf803f5fbef1,0x3f7ebf673f090000,0xbf393e793ea1bf46,
0xbf653f043cc9bf0e,0x3e603eacbf4a3f7f,0xbe893f3ebf7c3f6d,0x3f6abf7d3f42be95,0x3f7fbf4e3eb83e48,0xbf133d493efcbf62,0xbdfbbedb3f58bf80,0xbf313f78bf733f22,
0x3e483ec4bf553f80,0x3f0ebf6d3f7bbf35,0xbf7b3f6dbf0e0000,0x3f55bec4be483f35,0xbe48bec43f55bf80,0xbf0e3f6dbf7b3f35,0x3f7bbf6d3f0e0000,0xbf553ec43e48bf35,
0x3f7bbf6d3f0e8000,0xbf553ec43e48bf35,0x3e483ec4bf553f80,0x3f0ebf6d3f7bbf35,0xbf7b3f6dbf0e8000,0x3f55bec4be483f35,0xbe48bec43f55bf80,0xbf0e3f6dbf7b3f35,
0xbee6be163f31bf7b,0xbe603f3ebf7e3f62,0xbf773f71bf130000,0x3f6abf04bd973f22,0x3f42be79beb83f55,0xbe2fbedb3f5fbf7f,0x3f4abf803f58bec4,0xbf803f4ebea1be95,
0xbf653f7dbf393e48,0x3f7abf2c3dfb3ef1,0x3e893eacbf513f80,0x3ecfbf5c3f7fbf46,0x3f27bf783f6fbf0e,0xbf7c3f67befcbdc9,0xbf1d3d493f09bf6d,0xbcc93f18bf733f75,
0x3f67bef1be163f35,0xbf04bdc93f2cbf7b,0xbd493f22bf783f6d,0x3f18bf753f71bf0e,0xbeacbe953f4ebf80,0xbe793f46bf803f55,0x3f3ebf7f3f5cbec4,0xbf7d3f62bedbbe48,
0x3edbbf623f7dbf35,0xbf5c3f7fbf3e3e48,0x3f80bf463e793ec4,0xbf4e3e953eacbf55,0xbf713f75bf188000,0x3f78bf223d493f0e,0xbf2c3dc93f04bf6d,0x3e163ef1bf673f7b,
0xbf513f80bf423e48,0x3f7ebf5c3eb83e95,0x3cc93f18bf773f6d,0x3ee6bf673f7abf22,0x3f58beacbea13f55,0xbefcbe163f39bf7f,0x3f6abf783f1d0000,0xbf7f3f3ebe2fbef1,
0x3f133d49bf273f7b,0xbdfbbf043f6fbf75,0x3f80bf4e3e893ec4,0xbf653edb3e60bf46,0x3f09bf713f73bf0e,0xbf5f3f7dbf313dc9,0xbecfbe793f4abf80,0xbd973f2cbf7c3f62,
0x3ef13e48bf463f80,0xbdc9bf0e3f75bf6d,0xbe953f55bf7f3f35,0x3f22bf7b3f62bec4,0xbf623f7bbf220000,0x3f7fbf553e953ec4,0xbf753f0e3dc9bf35,0x3f46be48bef13f6d,
0x3f62bf7b3f228000,0xbf7f3f55be95bec4,0x3f75bf0ebdc93f35,0xbf463e483ef1bf6d,0x3ef13e48bf463f80,0xbdc9bf0e3f75bf6d,0xbe953f55bf7f3f35,0x3f22bf7b3f62bec4,
0xbf803f3ebdfbbf0e,0x3f73bf04be2f3f46,0xbf583f7dbf270000,0x3f77bf673ecf3e95,0xbeb8beac3f5fbf7b,0x3d973f18bf7a3f62,0xbf513e793ee6bf6d,0x3f1d3d49bf313f7f,
0xbcc93f2cbf7e3f55,0x3ea1bf5c3f7cbf22,0x3f093e16bf423f80,0xbe89bedb3f6abf75,0xbf6f3f71befcbe48,0x3f7fbf4e3e603ef1,0xbf133f78bf653ec4,0x3f4abf803f39bdc9,
0x3e16bf463f80bf35,0xbeac3f62bf783f0e,0x3f04bf753f67bec4,0xbf2c3f7fbf4e3e48,0xbf18bdc93f3ebf80,0x3edb3e95bf5c3f7b,0xbe79bef13f71bf6d,0x3d493f22bf7d3f55,
0xbf7d3f223d49bf35,0x3f71bef1be793f55,0xbf5c3e953edbbf6d,0x3f3ebdc9bf183f7b,0xbf4e3f7fbf2c8000,0x3f67bf753f043e48,0xbf783f62beacbec4,0x3f80bf463e163f0e,
0x3f7ebf4e3e2f3f0e,0xbf803f3ebd97bf22,0x3f73bf673eb83ec4,0xbf7a3f5cbe89bef1,0x3f5fbf783f093e48,0xbf6a3f71bee6be95,0x3f42bf803f310000,0xbf513f7dbf1dbdc9,
0xbdfbbf183f7cbf55,0x3cc93f2cbf7f3f46,0xbea1bedb3f6fbf6d,0x3e603f04bf773f62,0xbefcbe793f58bf7b,0x3ecf3eacbf653f75,0xbf27bd493f39bf80,0x3f133e16bf4a3f7f,
0xbf3500003f353f80,0x3f350000bf35bf80,0xbf3500003f353f80,0x3f350000bf35bf80,0xbf3500003f353f80,0x3f350000bf35bf80,0xbf3500003f353f80,0x3f350000bf35bf80,
0xbf35bf80bf358000,0x3f353f803f358000,0xbf35bf80bf358000,0x3f353f803f358000,0xbf35bf80bf358000,0x3f353f803f358000,0xbf35bf80bf358000,0x3f353f803f358000,
0xbf5f3f5cbf583f55,0xbf6a3f67bf653f62,0xbf423f3ebf393f35,0xbf513f4ebf4a3f46,0xbf7e3f7dbf7c3f7b,0xbf803f80bf7f3f7f,0xbf733f71bf6f3f6d,0xbf7a3f78bf773f75,
0xbefc3f04bf093f0e,0xbecf3edbbee63ef1,0xbf273f2cbf313f35,0xbf133f18bf1d3f22,0xbdfb3e16be2f3e48,0xbcc93d49bd973dc9,0xbea13eacbeb83ec4,0xbe603e79be893e95,
0xbf4e3f46bf3e3f35,0xbf673f62bf5c3f55,0xbf783f75bf713f6d,0xbf803f7fbf7d3f7b,0xbe163dc9bd490000,0xbeac3e95be793e48,0xbf043ef1bedb3ec4,0xbf2c3f22bf183f0e,
0xbf183f22bf2c3f35,0xbedb3ef1bf043f0e,0xbe793e95beac3ec4,0xbd493dc9be163e48,0xbf7d3f7fbf803f80,0xbf713f75bf783f7b,0xbf5c3f62bf673f6d,0xbf3e3f46bf4e3f55,
0xbf6f3f67bf5f3f55,0xbf7f3f7dbf7a3f75,0xbf133f04bee63ec4,0xbf4a3f3ebf313f22,0xbcc9bd493dfbbe48,0xbea13e79be2f3dc9,0x3f09bf183f27bf35,0x3e89beac3ecfbef1,
0xbeb83edbbefc3f0e,0xbd973e16be603e95,0xbf513f5cbf653f6d,0xbf1d3f2cbf393f46,0xbf803f80bf7e3f7b,0xbf733f78bf7c3f7f,0xbf583f4ebf423f35,0xbf773f71bf6a3f62,
0x3f75bf7b3f7fbf80,0x3f46bf553f62bf6d,0x3ef1bf0e3f22bf35,0x3dc9be483e95bec4,0xbe953e48bdc90000,0xbf223f0ebef13ec4,0xbf623f55bf463f35,0xbf7f3f7bbf753f6d,
0xbe953e48bdc98000,0xbf223f0ebef13ec4,0xbf623f55bf463f35,0xbf7f3f7bbf753f6d,0xbf753f7bbf7f3f80,0xbf463f55bf623f6d,0xbef13f0ebf223f35,0xbdc93e48be953ec4,
0x3f58bf673f73bf7b,0x3efcbf183f31bf46,0x3f6abf5c3f4abf35,0x3f7fbf803f7cbf75,0xbf513f3ebf273f0e,0xbf7e3f78bf6f3f62,0x3cc9be163e89bec4,0xbee63eacbe603dc9,
0xbf093edbbea13e48,0xbf5f3f4ebf393f22,0x3ecfbf043f1dbf35,0xbd97bd493e2fbe95,0xbf133f2cbf423f55,0xbdfb3e79beb83ef1,0xbf803f7dbf773f6d,0xbf653f71bf7a3f7f,
0x3eacbef13f18bf35,0xbe793dc93d49be48,0xbf3e3f22bf043ec4,0xbf7d3f75bf673f55,0x3edbbe953e160000,0x3f5cbf463f2cbf0e,0x3f80bf7f3f78bf6d,0x3f4ebf623f71bf7b,
0xbf713f62bf4e3f35,0xbf783f7fbf803f7b,0xbf2c3f46bf5c3f6d,0xbe163e95bedb3f0e,0x3f67bf753f7dbf80,0x3f04bf223f3ebf55,0xbd49bdc93e79bec4,0xbf183ef1beac3e48,
0xbf273f04beb83e48,0xbf7c3f71bf5f3f46,0x3f1dbf3e3f58bf6d,0xbcc9be163ea1bef1,0x3f65bf4e3f31bf0e,0x3f7abf803f7ebf75,0xbe893edbbf133f35,0x3ecfbe793d973dc9,
0xbf423f5cbf6f3f7b,0xbe2f3eacbefc3f22,0xbf4a3f2cbf093ec4,0xbf803f7dbf733f62,0x3ee6bf183f39bf55,0xbe603d493dfbbe95,0x3f77bf673f51bf35,0x3f6abf783f7fbf7f,
0xbf553f6dbf7b3f80,0xbe483ec4bf0e3f35,0x3f0ebec43e480000,0x3f7bbf6d3f55bf35,0x3f55bf6d3f7bbf80,0x3e48bec43f0ebf35,0xbf0e3ec4be480000,0xbf7b3f6dbf553f35,
0x3f0ebec43e488000,0x3f7bbf6d3f55bf35,0x3f55bf6d3f7bbf80,0x3e48bec43f0ebf35,0xbf0e3ec4be488000,0xbf7b3f6dbf553f35,0xbf553f6dbf7b3f80,0xbe483ec4bf0e3f35,
0x3d973e16beb83f0e,0x3f51bf2c3efcbe95,0xbf7e3f71bf583f35,0xbf393f5cbf733f7f,0xbee63e79bcc9be48,0xbf7a3f67bf4a3f22,0x3f77bf803f7cbf6d,0x3ecfbf183f42bf62,
0x3f7fbf7d3f6fbf55,0x3f13bf3e3f5fbf75,0xbdfb3eacbf093f35,0x3f31bf043ea1bdc9,0xbf653f78bf803f7b,0xbe603edbbf1d3f46,0xbe893d493e2fbec4,0xbf6a3f4ebf273ef1,
0x3f80bf753f5cbf35,0x3f18bf463f67bf7b,0xbeac3dc93e16bec4,0xbf783f62bf3e3f0e,0xbf2c3ef1be790000,0xbf7d3f7fbf713f55,0xbedb3f22bf4e3f6d,0x3f04be953d493e48,
0x3d49be953f04bf35,0xbf4e3f22bedb3e48,0xbf713f7fbf7d3f6d,0xbe793ef1bf2c3f55,0xbf3e3f62bf783f80,0x3e163dc9beac3f0e,0x3f67bf463f18bec4,0x3f5cbf753f80bf7b,
0xbe60bd493ea1bf0e,0xbf773f5cbf313ef1,0x3f6fbf4e3f1dbec4,0x3f42bf673f7cbf7f,0xbf513f71bf7f3f7b,0x3dfb3e16becf3f22,0xbcc9be793efcbf35,0xbf653f3ebf093e95,
0xbf7a3f80bf733f55,0xbe893f04bf393f62,0x3eb8bf183f4abf6d,0xbf273edbbe2fbdc9,0x3f13beac3d973e48,0x3f7ebf7d3f6abf46,0xbf803f78bf5f3f35,0xbee63f2cbf583f75,
0x3f22bf553f75bf80,0xbef13e483dc9bec4,0xbf7f3f7bbf623f35,0xbe953f0ebf463f6d,0x3f46bf0e3e950000,0x3f62bf7b3f7fbf6d,0xbdc9be483ef1bf35,0xbf753f55bf223ec4,
0xbf463f0ebe958000,0xbf623f7bbf7f3f6d,0x3dc93e48bef13f35,0x3f75bf553f22bec4,0x3f22bf553f75bf80,0xbef13e483dc9bec4,0xbf7f3f7bbf623f35,0xbe953f0ebf463f6d,
0xbf6a3f3ebefc3e48,0xbf273f5cbf7a3f7f,0x3f7cbf7d3f65bf35,0x3dfbbedb3f31bf62,0x3cc9beac3f1dbf55,0xbf733f4ebf133e95,0x3f09be79bd973ec4,0x3f77bf803f6fbf46,
0xbecf3f2cbf5f3f7b,0x3f42bf043e603dc9,0xbe2fbe163ee6bf35,0xbf7e3f67bf393ef1,0xbf803f71bf4a3f0e,0xbea13f18bf513f75,0x3f58bf783f7fbf6d,0xbe89bd493eb8bf22,
0x3e793dc9bedb3f35,0x3f80bf753f4ebf0e,0x3e16bef13f3ebf6d,0xbf713f46bf043e48,0x3f5cbf223eac0000,0x3f2cbf623f7dbf7b,0xbf183e953d49bec4,0xbf673f7fbf783f55,
0x3f78bf7f3f67bf35,0xbd49be953f18bf55,0xbf7d3f62bf2c3ec4,0xbeac3f22bf5c3f7b,0x3f04bf463f71bf80,0xbf3e3ef1be16be48,0xbf4e3f75bf803f6d,0x3edbbdc9be793f0e,
0x3e89bf183f58bf7b,0xbf6f3f3ebee63dc9,0xbd973edbbf393f6d,0x3f7cbf5c3f1dbe95,0xbdfbbe793f13bf55,0xbf803f71bf423ef1,0x3ea13d49becf3f35,0x3f7abf7d3f5fbf22,
0xbf773f4ebf093e48,0xbeb83f2cbf653f7f,0x3f7fbf673f31bec4,0x3e2fbf043f4abf75,0xbf7e3f78bf513f0e,0x3cc93eacbf273f62,0x3f73bf803f6abf35,0xbe60be163efcbf46,
0xbec43f35bf6d3f80,0x3f6dbf353ec40000,0x3ec4bf353f6dbf80,0xbf6d3f35bec40000,0xbec43f35bf6d3f80,0x3f6dbf353ec40000,0x3ec4bf353f6dbf80,0xbf6d3f35bec40000,
0x3f6dbf353ec48000,0x3ec4bf353f6dbf80,0xbf6d3f35bec48000,0xbec43f35bf6d3f80,0x3f6dbf353ec48000,0x3ec4bf353f6dbf80,0xbf6d3f35bec48000,0xbec43f35bf6d3f80,
0x3f4abf783f7cbf55,0xbf313eac3d97bef1,0xbf653f80bf6f3f35,0x3f09be16be893f22,0x3efcbf4e3f7abf7b,0xbf6a3f2cbea1bdc9,0xbf273f67bf803f6d,0x3f51bf043dfb3e95,
0xbf1d3e793e2fbf0e,0xbf393f71bf7f3f62,0x3ee6bd49beb83f35,0x3f58bf7d3f77bf46,0xbf5f3f18be60be48,0xbecf3f3ebf733f7f,0x3f42bedb3cc93ec4,0x3f13bf5c3f7ebf75,
0xbf5c3f7fbf713f35,0x3f2cbe95be163f0e,0x3f18bf623f80bf6d,0xbf673f22be79be48,0xbf783f46bedb0000,0xbd493ef1bf4e3f7b,0x3f7dbf753f3ebec4,0xbeacbdc93f04bf55,
0x3f04bdc9beac3f35,0x3f3ebf753f7dbf55,0xbf4e3ef1bd49bec4,0xbedb3f46bf783f7b,0xbe793f22bf673f80,0x3f80bf623f18be48,0xbe16be953f2cbf6d,0xbf713f7fbf5c3f0e,
0x3f31bf713f7ebf55,0xbf653f18be2fbe95,0xbf7a3f78bf423ec4,0x3efcbd49becf3f46,0x3f6fbf2c3e893e48,0x3d97bf043f58bf7f,0xbf133e163ea1bf35,0xbf1d3f67bf803f62,
0xbf393eac3dfbbf0e,0xbee63f4ebf7c3f75,0x3e603e79bf273f6d,0x3f5fbf803f6abf22,0x3eb8bf3e3f77bf7b,0xbf7f3f5cbf093dc9,0xbf513f7dbf733f35,0x3f4abedbbcc93ef1,
0x3dc9bf0e3f62bf80,0xbf753f7bbf463ec4,0x3f22be48be953f35,0x3ef1bf553f7fbf6d,0xbf7f3f55bef10000,0x3e953e48bf223f6d,0x3f46bf7b3f75bf35,0xbf623f0ebdc9bec4,
0xbf7f3f55bef18000,0x3e953e48bf223f6d,0x3f46bf7b3f75bf35,0xbf623f0ebdc9bec4,0xbdc93f0ebf623f80,0x3f75bf7b3f46bec4,0xbf223e483e95bf35,0xbef13f55bf7f3f6d,
0x3e2f3eacbf423f7b,0x3f4abf7d3f6fbf22,0x3f39bf783f77bf35,0xbf733f2cbe60be95,0x3f58bf803f65bf0e,0xbf5f3f04bcc9bef1,0xbf6a3f18bdfbbec4,0x3d973edbbf513f7f,
0x3f7cbf713f27be48,0xbf1d3e163eb8bf46,0xbf313e793e89bf35,0xbea13f3ebf7a3f75,0xbf093d493ee6bf55,0xbefc3f5cbf803f62,0xbecf3f4ebf7e3f6d,0x3f7fbf673f13bdc9,
0xbf3e3e953e79bf35,0xbe163f22bf713f7b,0x3f67bf7f3f4ebec4,0xbf5c3ef13d49bf0e,0x3f80bf623f040000,0xbf183dc93edbbf55,0xbeac3f46bf7d3f6d,0x3f78bf753f2cbe48,
0xbf2c3f75bf783f35,0x3f7dbf463eac3e48,0xbedbbdc93f18bf6d,0xbf043f62bf803f55,0xbd49bef13f5cbf80,0xbf4e3f7fbf673f0e,0x3f71bf223e163ec4,0xbe79be953f3ebf7b,
0x3f73bf783f31be48,0xbf583edb3dfbbf22,0xbefcbd493f13bf6d,0xbeb83f4ebf7f3f62,0xbf423f7dbf6a3f0e,0x3f7cbf3e3e893e95,0x3f4abeacbe603f35,0xbcc9bf043f65bf7f,
0xbea1be793f39bf7b,0xbf093f67bf7e3f46,0xbf5f3f80bf513ec4,0x3f6fbf183d973ef1,0x3f27be16becf3f55,0x3e2fbf2c3f77bf75,0x3f1dbf713f7abf35,0xbf803f5cbee6bdc9,
0x3e483ec4bf553f80,0x3f0ebf6d3f7bbf35,0xbf7b3f6dbf0e0000,0x3f55bec4be483f35,0xbe48bec43f55bf80,0xbf0e3f6dbf7b3f35,0x3f7bbf6d3f0e0000,0xbf553ec43e48bf35,
0x3f7bbf6d3f0e8000,0xbf553ec43e48bf35,0x3e483ec4bf553f80,0x3f0ebf6d3f7bbf35,0xbf7b3f6dbf0e8000,0x3f55bec4be483f35,0xbe48bec43f55bf80,0xbf0e3f6dbf7b3f35,
0xbf733f18bcc9bf0e,0x3f093d49bf1d3f75,0xbefc3f67bf7c3f35,0x3f6fbf783f27bdc9,0x3f7fbf5c3ecf3e48,0xbf513eac3e89bf46,0x3dfbbf2c3f7abf6d,0xbf393f7dbf653ef1,
0xbea13f4ebf803f55,0x3f58bf803f4abe95,0x3f5fbedbbe2f3f35,0xbeb8be793f42bf7f,0xbd97bf043f6abf7b,0xbf133f71bf773f22,0xbf7e3f3ebe60bec4,0x3f31be16bee63f62,
0x3edbbf623f7dbf35,0xbf5c3f7fbf3e3e48,0x3f80bf463e793ec4,0xbf4e3e953eacbf55,0xbf713f75bf180000,0x3f78bf223d493f0e,0xbf2c3dc93f04bf6d,0x3e163ef1bf673f7b,
0xbf673ef13e16bf35,0x3f043dc9bf2c3f7b,0x3d49bf223f78bf6d,0xbf183f75bf713f0e,0x3eac3e95bf4e3f80,0x3e79bf463f80bf55,0xbf3e3f7fbf5c3ec4,0x3f7dbf623edb3e48,
0x3f7cbf2c3d973f0e,0xbf4a3e793ecfbf62,0x3f31bf7d3f5fbec4,0xbf733f71bf09bdc9,0xbe60bedb3f65bf7b,0xbe893f4ebf803f46,0xbf6f3f043dfbbf35,0x3f27bd49bf133f75,
0x3e2fbf3e3f7fbf55,0xbf1d3f78bf6a3ef1,0xbf393e163efcbf6d,0x3ea13eacbf583f7f,0xbf7a3f67bee6be48,0x3f77bf18bcc93f22,0xbeb83f5cbf7e3f35,0x3f42bf803f51be95,
0xbef1be483f46bf80,0x3dc93f0ebf753f6d,0x3e95bf553f7fbf35,0xbf223f7bbf623ec4,0x3f62bf7b3f220000,0xbf7f3f55be95bec4,0x3f75bf0ebdc93f35,0xbf463e483ef1bf6d,
0xbf623f7bbf228000,0x3f7fbf553e953ec4,0xbf753f0e3dc9bf35,0x3f46be48bef13f6d,0xbef1be483f46bf80,0x3dc93f0ebf753f6d,0x3e95bf553f7fbf35,0xbf223f7bbf623ec4,
0x3f39bf803f4abe48,0xbf653f78bf13bdc9,0x3e60bf4e3f7fbf35,0xbefc3f71bf6f3ef1,0x3f6abedbbe893f55,0xbf423e163f09bf75,0x3f7cbf5c3ea13ec4,0xbf7e3f2cbcc9bf22,
0xbf313d493f1dbf7b,0x3ee63e79bf513f7f,0xbf7a3f183d97bf35,0x3f5fbeacbeb83f62,0x3ecfbf673f77bf0e,0xbf273f7dbf583e95,0xbe2fbf043f73bf6d,0xbdfb3f3ebf803f46,
0x3f7dbf22bd493f35,0xbf713ef13e79bf55,0x3f5cbe95bedb3f6d,0xbf3e3dc93f18bf7b,0x3f4ebf7f3f2c0000,0xbf673f75bf04be48,0x3f78bf623eac3ec4,0xbf803f46be16bf0e,
0x3e16bf463f80bf35,0xbeac3f62bf783f0e,0x3f04bf753f67bec4,0xbf2c3f7fbf4e3e48,0xbf18bdc93f3ebf80,0x3edb3e95bf5c3f7b,0xbe79bef13f71bf6d,0x3d493f22bf7d3f55,
0x3f4abe16bf133f7b,0xbf393d493f27bf7f,0x3f65beacbecf3f6d,0xbf583e793efcbf75,0x3f77bf04be603f55,0xbf6f3edb3ea1bf62,0x3f7fbf2cbcc93f35,0xbf7c3f183dfbbf46,
0x3f1dbf7d3f51be48,0xbf313f80bf423dc9,0x3ee6bf713f6abec4,0xbf093f78bf5f3e95,0x3e89bf5c3f7abf0e,0xbeb83f67bf733ef1,0x3d97bf3e3f80bf35,0xbe2f3f4ebf7e3f22,
0x3f350000bf353f80,0xbf3500003f35bf80,0x3f350000bf353f80,0xbf3500003f35bf80,0x3f350000bf353f80,0xbf3500003f35bf80,0x3f350000bf353f80,0xbf3500003f35bf80,
0xbf353f80bf358000,0x3f35bf803f358000,0xbf353f80bf358000,0x3f35bf803f358000,0xbf353f80bf358000,0x3f35bf803f358000,0xbf353f80bf358000,0x3f35bf803f358000,
0x3f77be79bf7a3e48,0x3f6fbeacbf733e95,0x3f7fbd49bf800000,0x3f7cbe16bf7e3dc9,0x3f4abf18bf513f0e,0x3f39bf2cbf423f22,0x3f65bedbbf6a3ec4,0x3f58bf04bf5f3ef1,
0xbe89bf783e603f7b,0xbeb8bf713ea13f75,0xbd97bf803cc93f80,0xbe2fbf7d3dfb3f7f,0xbf1dbf4e3f133f55,0xbf31bf3e3f273f46,0xbee6bf673ecf3f6d,0xbf09bf5c3efc3f62,
0x3f4e3f22bf3ebf35,0x3f673ef1bf5cbf0e,0x3f783e95bf71bec4,0x3f803dc9bf7dbe48,0x3e163f7fbd49bf80,0x3eac3f75be79bf7b,0x3f043f62bedbbf6d,0x3f2c3f46bf18bf55,
0x3f18bf46bf2c3f35,0x3edbbf62bf043f55,0x3e79bf75beac3f6d,0x3d49bf7fbe163f7b,0x3f7dbdc9bf808000,0x3f71be95bf783e48,0x3f5cbef1bf673ec4,0x3f3ebf22bf4e3f0e,
0x3ecf3f71be89bf7b,0x3f273f4ebf09bf62,0xbe2f3f783ea1bf6d,0x3dfb3f803cc9bf7f,0xbf313f2c3f4abf0e,0xbee63f5c3f13bf46,0xbf7a3e163f7f0000,0xbf5f3edb3f6fbe95,
0x3f6abeacbf773e48,0x3f42bf18bf583ef1,0x3f7c3e79bf73bec4,0x3f7ebd49bf80bdc9,0x3f393f3ebf1dbf55,0x3f653f04bf51bf22,0x3e603f7dbd97bf80,0x3efc3f67beb8bf75,
0xbe95bf7b3dc93f80,0xbf22bf553ef13f6d,0xbf62bf0e3f463f35,0xbf7fbe483f753ec4,0xbf753e483f7f0000,0xbf463f0e3f62bec4,0xbef13f553f22bf35,0xbdc93f7b3e95bf6d,
0xbf753e483f7f8000,0xbf463f0e3f62bec4,0xbef13f553f22bf35,0xbdc93f7b3e95bf6d,0x3e953f7bbdc9bf80,0x3f223f55bef1bf6d,0x3f623f0ebf46bf35,0x3f7f3e48bf75bec4,
0x3e60bf71bee63f55,0xbe89bf7d3cc93f7f,0x3f6fbe79bf7e0000,0x3f27bf2cbf513ef1,0xbf7c3d493f7f3e48,0xbf4a3f043f6abe95,0xbf31bf4e3efc3f6d,0xbf73bedb3f583f22,
0xbf7abeac3f653f0e,0xbf773e163f803dc9,0xbeb8bf783dfb3f80,0xbf42bf3e3f133f62,0x3e2f3f803d97bf7b,0x3f1d3f5cbecfbf75,0xbf393f183f5fbec4,0xbea13f673f09bf46,
0x3eacbf62bf183f35,0xbe79bf7fbd493f7b,0xbf3ebf463f043f6d,0xbf7dbe953f673f0e,0x3edb3f75be16bf80,0x3f5c3f22bf2cbf55,0x3f803dc9bf78bec4,0x3f4ebef1bf713e48,
0xbf71bef13f4e3f35,0xbf783dc93f803e48,0xbf2c3f223f5cbec4,0xbe163f753edbbf55,0x3f67be95bf7d8000,0x3f04bf46bf3e3f0e,0xbd49bf7fbe793f6d,0xbf18bf623eac3f7b,
0x3d97bf78becf3f55,0xbf13bf673e893f7f,0x3f7e3d49bf7abec4,0x3f31bf18bf653e95,0x3ea13f7d3cc9bf7b,0x3f583f2cbf1dbf62,0xbf5f3eac3f7c0000,0xbeb83f5c3f27bf22,
0xbf7fbe793f6a3f0e,0xbf513edb3f77bdc9,0xbdfbbf80be603f6d,0xbf39bf4e3ee63f75,0x3f73be16bf80be48,0x3f09bf3ebf4a3ef1,0x3efc3f71be2fbf80,0x3f6f3f04bf42bf46,
0xbf0ebf6d3e483f80,0xbf7bbec43f553f35,0xbf553ec43f7b0000,0xbe483f6d3f0ebf35,0x3f0e3f6dbe48bf80,0x3f7b3ec4bf55bf35,0x3f55bec4bf7b0000,0x3e48bf6dbf0e3f35,
0xbf553ec43f7b8000,0xbe483f6d3f0ebf35,0x3f0e3f6dbe48bf80,0x3f7b3ec4bf55bf35,0x3f55bec4bf7b8000,0x3e48bf6dbf0e3f35,0xbf0ebf6d3e483f80,0xbf7bbec43f553f35,
0xbf42bf4e3ecf3f7b,0xbf7cbd493f773ef1,0x3f4abedbbf7a0000,0x3cc9bf78bee63f46,0x3f733f04bf39bf55,0x3f58beacbf7ebdc9,0xbefc3f3e3f51bec4,0x3eb83f7d3d97bf75,
0xbf273f183f6abe48,0x3e2f3f803e89bf62,0xbf1dbf673e603f80,0xbf80be793f653f22,0x3ea1bf5cbf313f0e,0xbf09bf713dfb3f7f,0x3f5f3f2cbf13bf6d,0x3f6fbe16bf7fbe95,
0xbf80be953f5c3f35,0xbf183f223f67be48,0x3eac3f7f3e16bf6d,0x3f783ef1bf3ebf55,0x3f2c3f62be79bf80,0x3f7d3dc9bf71bf0e,0x3edbbf46bf4e3ec4,0xbf04bf753d493f7b,
0xbd493f753f04bf35,0x3f4e3f46bedbbf7b,0x3f71bdc9bf7dbec4,0x3e79bf62bf2c3f0e,0x3f3ebef1bf788000,0xbe16bf7fbeac3f55,0xbf67bf223f183f6d,0xbf5c3e953f803e48,
0xbf093f2c3f65be48,0x3efc3f783cc9bf75,0xbecfbf7dbdfb3f6d,0xbf7fbeac3f513f46,0x3f7c3edbbf42bf55,0x3f1dbf18bf6f3dc9,0xbf313f043f770000,0x3ea13f803e60bf62,
0x3f583f3ebee6bf7b,0x3f5fbe79bf80be95,0xbf6a3e163f7e3ec4,0xbd973f713f13bf22,0x3e2fbf67bf273f0e,0xbf4abf4e3eb83f7f,0x3f393f5cbe89bf80,0x3f73bd49bf7abef1,
0xbf46bf553e953f80,0xbf623e483f7f3ec4,0x3dc93f7b3ef1bf35,0x3f753f0ebf22bf6d,0x3f22bf0ebf750000,0xbef1bf7bbdc93f6d,0xbf7fbe483f623f35,0xbe953f553f46bec4,
0xbf223f0e3f758000,0x3ef13f7b3dc9bf6d,0x3f7f3e48bf62bf35,0x3e95bf55bf463ec4,0xbf46bf553e953f80,0xbf623e483f7f3ec4,0x3dc93f7b3ef1bf35,0x3f753f0ebf22bf6d,
0xbf6f3d493f773f0e,0x3d973f783f09bf22,0x3f13bf18bf730000,0xbf1dbf713cc93f75,0xbf31bf673dfb3f7b,0xbf653e163f7c3ef1,0x3f7a3f04bf27bf6d,0x3efcbf2cbf6a3dc9,
0x3eb83f803e89bf55,0x3f7f3e79bf58bf46,0xbf51bf4e3ea13f80,0xbf4a3eac3f803e95,0xbf393edb3f7e3e48,0x3ee63f7d3e2fbf62,0x3e60bf5cbf423ec4,0xbf5fbf3e3ecf3f7f,
0x3e793f7f3edbbf35,0x3f803e95bf4ebf55,0x3e16bf62bf3e3ec4,0xbf71bf223f043f7b,0x3f5c3f46beacbf80,0x3f2cbef1bf7dbe48,0xbf18bf75bd493f6d,0xbf673dc93f783f0e,
0x3f783dc9bf67bf35,0xbd49bf75bf183f0e,0xbf7dbef13f2c3f6d,0xbeac3f463f5cbe48,0x3f04bf22bf718000,0xbf3ebf623e163f7b,0xbf4e3e953f803ec4,0x3edb3f7f3e79bf55,
0x3f5fbe16bf7abf0e,0xbecfbf80bea13f46,0xbf423eac3f803ec4,0x3f133f783dfbbf62,0x3f1dbf04bf7cbe48,0xbf39bf673d973f75,0xbee63f2c3f6f0000,0x3f583f4ebe89bf7f,
0xbefcbf7dbe603f55,0xbf6a3d493f733f22,0x3f273f713cc9bf6d,0x3f51be79bf7ebef1,0xbf4abf5c3e2f3f7b,0xbf313edb3f7f3e95,0x3f653f3ebeb8bf80,0x3f09bf18bf77bdc9,
0xbf6dbf353ec43f80,0xbec43f353f6d0000,0x3f6d3f35bec4bf80,0x3ec4bf35bf6d0000,0xbf6dbf353ec43f80,0xbec43f353f6d0000,0x3f6d3f35bec4bf80,0x3ec4bf35bf6d0000,
0xbec43f353f6d8000,0x3f6d3f35bec4bf80,0x3ec4bf35bf6d8000,0xbf6dbf353ec43f80,0xbec43f353f6d8000,0x3f6d3f35bec4bf80,0x3ec4bf35bf6d8000,0xbf6dbf353ec43f80,
0xbdfb3f5c3f51be48,0x3f803edbbf27bf75,0x3ea1bf3ebf6a0000,0xbf7abf183efc3f7f,0x3e893f7d3f09bf0e,0x3f6f3d49bf65bf46,0xbd97bf71bf313ec4,0xbf7cbe793f4a3f62,
0x3f7e3f04bf13bf7b,0x3cc9bf67bf423e95,0xbf73bf2c3ecf3f80,0xbe603f4e3f5fbdc9,0x3f773e16bf58bf55,0xbeb8bf80bee63f22,0xbf7fbeac3f393f6d,0x3e2f3f783f1dbef1,
0x3f5cbdc9bf71bf35,0xbf2cbf75be163f55,0xbf183ef13f803ec4,0x3f673f46be79bf7b,0x3f783f22bedbbf80,0x3d49bf62bf4e3e48,0xbf7dbe953f3e3f6d,0x3eac3f7f3f04bf0e,
0xbf04bf7fbeac3f35,0xbf3e3e953f7d3f0e,0x3f4e3f62bd49bf6d,0x3edbbf22bf78be48,0x3e79bf46bf678000,0xbf80bef13f183f7b,0x3e163f753f2cbec4,0x3f713dc9bf5cbf55,
0xbf80bedb3f1d3f7b,0x3ea13f7d3f13bef1,0x3f583f5cbd97bf6d,0x3e89bf3ebf6fbdc9,0xbecfbf80befc3f0e,0xbf423e793f7a3f22,0xbe2f3f4e3f650000,0x3f7e3eacbf31bf75,
0x3cc93f673f4abe48,0x3f733e16bf51bf62,0x3f09bf04bf7fbec4,0xbf77bf2c3eb83f7f,0xbf6abd493f5f3f55,0x3f273f783e60bf46,0x3f7c3f18bee6bf80,0xbdfbbf71bf393e95,
0xbf7fbf0e3ef13f80,0x3e953f7b3f22bec4,0x3f46be48bf75bf35,0xbf62bf553dc93f6d,0xbdc93f553f620000,0x3f753e48bf46bf6d,0xbf22bf7bbe953f35,0xbef13f0e3f7f3ec4,
0xbdc93f553f628000,0x3f753e48bf46bf6d,0xbf22bf7bbe953f35,0xbef13f0e3f7f3ec4,0x3f7f3f0ebef1bf80,0xbe95bf7bbf223ec4,0xbf463e483f753f35,0x3f623f55bdc9bf6d,
0x3f513f673d97bf55,0x3dfbbf4ebf6abdc9,0x3cc9bf5cbf5f0000,0xbf65bd493f583f62,0x3e60bf3ebf73be48,0xbf77be793f393f75,0xbf6fbe163f4a3f6d,0x3f423f713e2fbf46,
0x3f13bedbbf7fbf0e,0xbf7ebf183ecf3f7f,0xbf80bf043efc3f80,0x3ee63f803f09bef1,0xbf7abf2c3ea13f7b,0x3e893f783f31be95,0x3eb83f7d3f1dbec4,0x3f27beacbf7cbf22,
0xbf3ebf75be793f35,0xbe163f463f713e48,0x3f673dc9bf4ebf6d,0xbf5cbf62bd493f55,0x3f803ef1bf04bf80,0xbf18bf7fbedb3f0e,0xbeac3f223f7d3ec4,0x3f783e95bf2cbf7b,
0xbf2c3e953f783f35,0x3f7d3f22beacbf7b,0xbedbbf7fbf183ec4,0xbf043ef13f803f0e,0xbd49bf62bf5c8000,0xbf4e3dc93f673f55,0x3f713f46be16bf6d,0xbe79bf75bf3e3e48,
0x3f653f5c3cc9bf55,0xbe60bf71bf4a3dc9,0x3e89bf2cbf7cbec4,0xbf6abe163f423f75,0xbf7fbf183eb83f7b,0x3f133f803efcbef1,0x3dfb3f673f580000,0x3f31be79bf73bf46,
0x3ee6bf04bf80bf0e,0xbf7abeac3f1d3f7f,0xbf77bf3e3e2f3f6d,0x3ecf3f7d3f27be95,0xbd973f4e3f6f3e48,0x3f51bd49bf5fbf62,0x3f7e3edbbf09bf80,0xbf39bf78bea13f22,
0xbf7bbec43f0e3f80,0x3f553f6d3e48bf35,0xbe48bf6dbf550000,0xbf0e3ec43f7b3f35,0x3f7b3ec4bf0ebf80,0xbf55bf6dbe483f35,0x3e483f6d3f550000,0x3f0ebec4bf7bbf35,
0x3e483f6d3f558000,0x3f0ebec4bf7bbf35,0xbf7bbec43f0e3f80,0x3f553f6d3e48bf35,0xbe48bf6dbf558000,0xbf0e3ec43f7b3f35,0x3f7b3ec4bf0ebf80,0xbf55bf6dbe483f35,
0x3f653e16bf39bf7b,0xbf7abf3e3dfb3f62,0xbe89bf71bf510000,0xbecf3f043f7f3f22,0xbf273e793f6f3f55,0x3f7c3edbbefcbf7f,0x3f1d3f803f09bec4,0x3cc9bf4ebf73be95,
0xbee6bf7dbf313e48,0xbe603f2c3f7e3ef1,0xbf77beac3f133f80,0x3f6a3f5c3d97bf46,0x3f423f783eb8bf0e,0xbe2fbf67bf5fbdc9,0x3f4abd49bf58bf6d,0xbf80bf183ea13f75,
0xbedb3ef13f7d3f35,0x3f5c3dc9bf3ebf7b,0xbf80bf223e793f6d,0x3f4e3f753eacbf0e,0x3f713e95bf18bf80,0xbf78bf463d493f55,0x3f2c3f7f3f04bec4,0xbe16bf62bf67be48,
0x3f673f623e16bf35,0xbf04bf7fbf2c3e48,0xbd493f463f783ec4,0x3f18be95bf71bf55,0xbeacbf75bf4e8000,0xbe793f223f803f0e,0x3f3ebdc9bf5cbf6d,0xbf7dbef13edb3f7b,
0xbf13bf80bf273e48,0x3dfb3f5c3f6f3e95,0xbf80bf183e893f6d,0x3f653f673e60bf22,0xbf093eac3f733f55,0x3f5f3e16bf31bf7f,0x3ecf3f783f4a0000,0x3d97bf3ebf7cbef1,
0xbf51bd493f423f7b,0x3f7e3f04beb8bf75,0x3cc93f4e3f773ec4,0x3ee6bedbbf7abf46,0x3f583f713ea1bf0e,0xbefcbf7dbf393dc9,0x3f6a3e79bf1dbf80,0xbf7fbf2c3e2f3f62,
0xbf62be483f223f80,0x3f7f3f0ebe95bf6d,0xbf75bf55bdc93f35,0x3f463f7b3ef1bec4,0xbef1bf7bbf460000,0x3dc93f553f753ec4,0x3e95bf0ebf7fbf35,0xbf223e483f623f6d,
0x3ef13f7b3f468000,0xbdc9bf55bf75bec4,0xbe953f0e3f7f3f35,0x3f22be48bf62bf6d,0xbf62be483f223f80,0x3f7f3f0ebe95bf6d,0xbf75bf55bdc93f35,0x3f463f7b3ef1bec4,
0x3cc9bf3ebf7ebf0e,0xbea13f043f7c3f46,0xbf09bf7dbf420000,0x3e893f673f6a3e95,0x3f6f3eacbefcbf7b,0xbf7fbf183e603f62,0x3f13be79bf65bf6d,0xbf4abd493f393f7f,
0xbf80bf2c3dfb3f55,0x3f733f5c3e2fbf22,0xbf58be163f273f80,0x3f773edbbecfbf75,0xbeb8bf71bf5fbe48,0x3d973f4e3f7a3ef1,0xbf51bf78bee63ec4,0x3f1d3f803f31bdc9,
0x3f7d3f463d49bf35,0xbf71bf62be793f0e,0x3f5c3f753edbbec4,0xbf3ebf7fbf183e48,0x3f4e3dc9bf2cbf80,0xbf67be953f043f7b,0x3f783ef1beacbf6d,0xbf80bf223e163f55,
0x3e16bf22bf80bf35,0xbeac3ef13f783f55,0x3f04be95bf67bf6d,0xbf2c3dc93f4e3f7b,0xbf18bf7fbf3e8000,0x3edb3f753f5c3e48,0xbe79bf62bf71bec4,0x3d493f463f7d3f0e,
0x3dfb3f4e3f7c3f0e,0xbcc9bf3ebf7fbf22,0x3ea13f673f6f3ec4,0xbe60bf5cbf77bef1,0x3efc3f783f583e48,0xbecfbf71bf65be95,0x3f273f803f390000,0xbf13bf7dbf4abdc9,
0x3f7e3f18be2fbf55,0xbf80bf2c3d973f46,0x3f733edbbeb8bf6d,0xbf7abf043e893f62,0x3f5f3e79bf09bf7b,0xbf6abeac3ee63f75,0x3f423d49bf31bf80,0xbf51be163f1d3f7f,
0x3f350000bf353f80,0xbf3500003f35bf80,0x3f350000bf353f80,0xbf3500003f35bf80,0x3f350000bf353f80,0xbf3500003f35bf80,0x3f350000bf353f80,0xbf3500003f35bf80,
0xbf353f80bf358000,0x3f35bf803f358000,0xbf353f80bf358000,0x3f35bf803f358000,0xbf353f80bf358000,0x3f35bf803f358000,0xbf353f80bf358000,0x3f35bf803f358000,
0x3efcbf5cbf093f55,0x3ecfbf67bee63f62,0x3f27bf3ebf313f35,0x3f13bf4ebf1d3f46,0x3dfbbf7dbe2f3f7b,0x3cc9bf80bd973f7f,0x3ea1bf71beb83f6d,0x3e60bf78be893f75,
0xbf5fbf043f583f0e,0xbf6abedb3f653ef1,0xbf42bf2c3f393f35,0xbf51bf183f4a3f22,0xbf7ebe163f7c3e48,0xbf80bd493f7f3dc9,0xbf73beac3f6f3ec4,0xbf7abe793f773e95,
0x3f18bf46bf2c3f35,0x3edbbf62bf043f55,0x3e79bf75beac3f6d,0x3d49bf7fbe163f7b,0x3f7dbdc9bf800000,0x3f71be95bf783e48,0x3f5cbef1bf673ec4,0x3f3ebf22bf4e3f0e,
0xbf4ebf223f3e3f35,0xbf67bef13f5c3f0e,0xbf78be953f713ec4,0xbf80bdc93f7d3e48,0xbe16bf7f3d493f80,0xbeacbf753e793f7b,0xbf04bf623edb3f6d,0xbf2cbf463f183f55,
0x3eb8bf67befc3f55,0x3d97bf7dbe603f75,0x3f51bf04bf653ec4,0x3f1dbf3ebf393f22,0x3f803d49bf7ebe48,0x3f73be79bf7c3dc9,0x3f583f18bf42bf35,0x3f773eacbf6abef1,
0xbf6fbedb3f5f3f0e,0xbf7fbe163f7a3e95,0xbf13bf5c3ee63f6d,0xbf4abf2c3f313f46,0xbcc9bf80bdfb3f7b,0xbea1bf783e2f3f7f,0x3f09bf4ebf273f35,0x3e89bf71becf3f62,
0x3e953f7bbdc9bf80,0x3f223f55bef1bf6d,0x3f623f0ebf46bf35,0x3f7f3e48bf75bec4,0x3f75be48bf7f0000,0x3f46bf0ebf623ec4,0x3ef1bf55bf223f35,0x3dc9bf7bbe953f6d,
0x3f75be48bf7f8000,0x3f46bf0ebf623ec4,0x3ef1bf55bf223f35,0x3dc9bf7bbe953f6d,0xbe95bf7b3dc93f80,0xbf22bf553ef13f6d,0xbf62bf0e3f463f35,0xbf7fbe483f753ec4,
0x3f093f67bea1bf7b,0x3f5f3f18bf39bf46,0xbecf3f5c3f1dbf35,0x3d973f803e2fbf75,0x3f13bf3ebf423f0e,0x3dfbbf78beb83f62,0x3f803e16bf77bec4,0x3f65beacbf7a3dc9,
0x3f58bedbbf733e48,0x3efcbf4ebf313f22,0x3f6a3f04bf4abf35,0x3f7f3d49bf7cbe95,0xbf51bf2c3f273f55,0xbf7ebe793f6f3ef1,0x3cc9bf7dbe893f6d,0xbee6bf713e603f7f,
0x3f713ef1bf4ebf35,0x3f78bdc9bf80be48,0x3f2cbf22bf5c3ec4,0x3e16bf75bedb3f55,0xbf673e953f7d0000,0xbf043f463f3ebf0e,0x3d493f7f3e79bf6d,0x3f183f62beacbf7b,
0x3eacbf62bf183f35,0xbe79bf7fbd493f7b,0xbf3ebf463f043f6d,0xbf7dbe953f673f0e,0x3edb3f75be16bf80,0x3f5c3f22bf2cbf55,0x3f803dc9bf78bec4,0x3f4ebef1bf713e48,
0x3f42bf04bf6f3e48,0x3e2fbf71befc3f46,0x3f4a3f3ebf09bf6d,0x3f803e16bf73bef1,0xbee63f4e3f39bf0e,0x3e603f803dfbbf75,0xbf77bedb3f513f35,0xbf6a3e793f7f3dc9,
0xbf27bf5c3eb83f7b,0xbf7cbeac3f5f3f22,0x3f1dbf2cbf583ec4,0xbcc9bf7dbea13f62,0x3f653f18bf31bf55,0x3f7abd49bf7ebe95,0xbe893f673f13bf35,0x3ecf3f78bd97bf7f,
0xbf0ebf6d3e483f80,0xbf7bbec43f553f35,0xbf553ec43f7b0000,0xbe483f6d3f0ebf35,0x3f0e3f6dbe48bf80,0x3f7b3ec4bf55bf35,0x3f55bec4bf7b0000,0x3e48bf6dbf0e3f35,
0xbf553ec43f7b8000,0xbe483f6d3f0ebf35,0x3f0e3f6dbe48bf80,0x3f7b3ec4bf55bf35,0x3f55bec4bf7b8000,0x3e48bf6dbf0e3f35,0xbf0ebf6d3e483f80,0xbf7bbec43f553f35,
0xbf7fbe163f6f3f0e,0xbf133f2c3f5fbe95,0x3dfbbf71bf093f35,0xbf31bf5c3ea13f7f,0x3f65be79bf80be48,0x3e60bf67bf1d3f22,0x3e893f803e2fbf6d,0x3f6a3f18bf27bf62,
0x3d973f7d3eb8bf55,0x3f513f3ebefcbf75,0xbf7ebeac3f583f35,0xbf393f043f73bdc9,0xbee6bf783cc93f7b,0xbf7abedb3f4a3f46,0x3f77bd49bf7cbec4,0x3ecfbf4ebf423ef1,
0xbd493f753f04bf35,0x3f4e3f46bedbbf7b,0x3f71bdc9bf7dbec4,0x3e79bf62bf2c3f0e,0x3f3ebef1bf780000,0xbe16bf7fbeac3f55,0xbf67bf223f183f6d,0xbf5c3e953f803e48,
0x3f803e95bf5cbf35,0x3f18bf22bf673e48,0xbeacbf7fbe163f6d,0xbf78bef13f3e3f55,0xbf2cbf623e793f80,0xbf7dbdc93f713f0e,0xbedb3f463f4ebec4,0x3f043f75bd49bf7b,
0x3f7a3d49bf73bf0e,0x3e89bf5cbf393ef1,0xbeb83f4e3f4abec4,0x3f273f67be2fbf7f,0xbf13bf713d973f7b,0xbf7ebe163f6a3f22,0x3f803e79bf5fbf35,0x3ee6bf3ebf583e95,
0xbe60bf80bea13f55,0xbf77bf043f313f62,0x3f6f3f18bf1dbf6d,0x3f42bedbbf7cbdc9,0xbf513eac3f7f3e48,0x3dfb3f7d3ecfbf46,0xbcc9bf78befc3f35,0xbf65bf2c3f093f75,
0x3f463f55be95bf80,0x3f62be48bf7fbec4,0xbdc9bf7bbef13f35,0xbf75bf0e3f223f6d,0xbf223f0e3f750000,0x3ef13f7b3dc9bf6d,0x3f7f3e48bf62bf35,0x3e95bf55bf463ec4,
0x3f22bf0ebf758000,0xbef1bf7bbdc93f6d,0xbf7fbe483f623f35,0xbe953f553f46bec4,0x3f463f55be95bf80,0x3f62be48bf7fbec4,0xbdc9bf7bbef13f35,0xbf75bf0e3f223f6d,
0x3ecfbf3ebf5f3e48,0xbf42bf5c3e603f7f,0x3e2f3f7d3ee6bf35,0x3f7e3edbbf39bf62,0x3f803eacbf4abf55,0x3ea1bf4ebf513e95,0xbf583e793f7f3ec4,0x3e893f803eb8bf46,
0xbf6abf2c3efc3f7b,0xbf273f043f7a3dc9,0x3f7c3e16bf65bf35,0x3dfbbf67bf313ef1,0x3cc9bf71bf1d3f0e,0xbf73bf183f133f75,0x3f093f783d97bf6d,0x3f773d49bf6fbf22,
0xbf78bdc93f673f35,0x3d493f753f18bf0e,0x3f7d3ef1bf2cbf6d,0x3eacbf46bf5c3e48,0xbf043f223f710000,0x3f3e3f62be16bf7b,0x3f4ebe95bf80bec4,0xbedbbf7fbe793f55,
0x3e793f7f3edbbf35,0x3f803e95bf4ebf55,0x3e16bf62bf3e3ec4,0xbf71bf223f043f7b,0x3f5c3f46beacbf80,0x3f2cbef1bf7dbe48,0xbf18bf75bd493f6d,0xbf673dc93f783f0e,
0x3f773f18bf09bf7b,0x3eb8bf3ebf653dc9,0xbf7fbedb3f313f6d,0xbe2f3f5c3f4abe95,0x3f7e3e79bf51bf55,0xbcc9bf71bf273ef1,0xbf73bd493f6a3f35,0x3e603f7d3efcbf22,
0x3e89bf4ebf583e48,0xbf6fbf2c3ee63f7f,0xbd973f673f39bec4,0x3f7c3f04bf1dbf75,0xbdfbbf78bf133f0e,0xbf80beac3f423f62,0x3ea13f803ecfbf35,0x3f7a3e16bf5fbf46,
0xbf6dbf353ec43f80,0xbec43f353f6d0000,0x3f6d3f35bec4bf80,0x3ec4bf35bf6d0000,0xbf6dbf353ec43f80,0xbec43f353f6d0000,0x3f6d3f35bec4bf80,0x3ec4bf35bf6d0000,
0xbec43f353f6d8000,0x3f6d3f35bec4bf80,0x3ec4bf35bf6d8000,0xbf6dbf353ec43f80,0xbec43f353f6d8000,0x3f6d3f35bec4bf80,0x3ec4bf35bf6d8000,0xbf6dbf353ec43f80,
0x3f1d3f783e2fbf55,0x3f39beacbf7fbef1,0xbee6bf80beb83f35,0xbf583e163f773f22,0x3f5f3f4ebe60bf7b,0x3ecfbf2cbf73bdc9,0xbf42bf673cc93f6d,0xbf133f043f7e3e95,
0x3f4abe79bf7cbf0e,0xbf31bf71bd973f62,0xbf653d493f6f3f35,0x3f093f7d3e89bf46,0x3efcbf18bf7abe48,0xbf6abf3e3ea13f7f,0xbf273edb3f803ec4,0x3f513f5cbdfbbf75,
0xbf04bf7fbeac3f35,0xbf3e3e953f7d3f0e,0x3f4e3f62bd49bf6d,0x3edbbf22bf78be48,0x3e79bf46bf670000,0xbf80bef13f183f7b,0x3e163f753f2cbec4,0x3f713dc9bf5cbf55,
0xbf5c3dc93f713f35,0x3f2c3f753e16bf55,0x3f18bef1bf80bec4,0xbf67bf463e793f7b,0xbf78bf223edb3f80,0xbd493f623f4ebe48,0x3f7d3e95bf3ebf6d,0xbeacbf7fbf043f0e,
0x3f393f713dfbbf55,0x3ee6bf18bf7cbe95,0xbe60bf78bf273ec4,0xbf5f3d493f6a3f46,0xbeb83f2c3f773e48,0x3f7f3f04bf09bf7f,0x3f51be16bf73bf35,0xbf4abf67bcc93f62,
0x3f31beacbf7ebf0e,0xbf65bf4e3e2f3f75,0xbf7abe793f423f6d,0x3efc3f803ecfbf22,0x3f6f3f3ebe89bf7b,0x3d97bf5cbf583dc9,0xbf13bf7dbea13f35,0xbf1d3edb3f803ef1,
0x3f7f3f0ebef1bf80,0xbe95bf7bbf223ec4,0xbf463e483f753f35,0x3f623f55bdc9bf6d,0x3dc9bf55bf620000,0xbf75be483f463f6d,0x3f223f7b3e95bf35,0x3ef1bf0ebf7fbec4,
0x3dc9bf55bf628000,0xbf75be483f463f6d,0x3f223f7b3e95bf35,0x3ef1bf0ebf7fbec4,0xbf7fbf0e3ef13f80,0x3e953f7b3f22bec4,0x3f46be48bf75bf35,0xbf62bf553dc93f6d,
0xbf7cbeac3f273f7b,0x3f1d3f7d3eb8bf22,0x3f313f783e89bf35,0x3ea1bf2cbf7abe95,0x3f093f803ee6bf0e,0x3efcbf04bf80bef1,0x3ecfbf18bf7ebec4,0xbf7fbedb3f133f7f,
0x3e2f3f713f42be48,0x3f4abe16bf6fbf46,0x3f39be79bf77bf35,0xbf73bf3e3e603f75,0x3f58bd49bf65bf55,0xbf5fbf5c3cc93f62,0xbf6abf4e3dfb3f6d,0x3d973f673f51bdc9,
0x3f2cbe95bf78bf35,0xbf7dbf223eac3f7b,0x3edb3f7f3f18bec4,0x3f04bef1bf80bf0e,0x3d493f623f5c0000,0x3f4ebdc9bf67bf55,0xbf71bf463e163f6d,0x3e793f753f3ebe48,
0xbf3ebf75be793f35,0xbe163f463f713e48,0x3f673dc9bf4ebf6d,0xbf5cbf62bd493f55,0x3f803ef1bf04bf80,0xbf18bf7fbedb3f0e,0xbeac3f223f7d3ec4,0x3f783e95bf2cbf7b,
0x3ea13f783f39be48,0x3f09bedbbf7ebf22,0x3f5f3d49bf51bf6d,0xbf6fbf4e3d973f62,0xbf27bf7dbecf3f0e,0xbe2f3f3e3f773e95,0xbf1d3eac3f7a3f35,0x3f803f04bee6bf7f,
0x3f733e79bf31bf7b,0xbf58bf67bdfb3f46,0xbefcbf80bf133ec4,0xbeb83f183f7f3ef1,0xbf423e163f6a3f55,0x3f7c3f2cbe89bf75,0x3f4a3f713e60bf35,0xbcc9bf5cbf65bdc9,
0xbf7bbec43f0e3f80,0x3f553f6d3e48bf35,0xbe48bf6dbf550000,0xbf0e3ec43f7b3f35,0x3f7b3ec4bf0ebf80,0xbf55bf6dbe483f35,0x3e483f6d3f550000,0x3f0ebec4bf7bbf35,
0x3e483f6d3f558000,0x3f0ebec4bf7bbf35,0xbf7bbec43f0e3f80,0x3f553f6d3e48bf35,0xbe48bf6dbf558000,0xbf0e3ec43f7b3f35,0x3f7b3ec4bf0ebf80,0xbf55bf6dbe483f35,
0x3ea1bf18bf80bf0e,0xbf58bd493f4a3f75,0xbf5fbf67be2f3f35,0x3eb83f783f42bdc9,0x3d973f5c3f6a3e48,0x3f13beacbf77bf46,0x3f7e3f2cbe60bf6d,0xbf31bf7dbee63ef1,
0xbf73bf4e3cc93f55,0x3f093f803f1dbe95,0xbefc3edb3f7c3f35,0x3f6f3e79bf27bf7f,0x3f7f3f04becfbf7b,0xbf51bf71be893f22,0x3dfbbf3ebf7abec4,0xbf393e163f653f62,
0x3f673f623e16bf35,0xbf04bf7fbf2c3e48,0xbd493f463f783ec4,0x3f18be95bf71bf55,0xbeacbf75bf4e0000,0xbe793f223f803f0e,0x3f3ebdc9bf5cbf6d,0xbf7dbef13edb3f7b,
0x3edbbef1bf7dbf35,0xbf5cbdc93f3e3f7b,0x3f803f22be79bf6d,0xbf4ebf75beac3f0e,0xbf71be953f183f80,0x3f783f46bd49bf55,0xbf2cbf7fbf043ec4,0x3e163f623f673e48,
0xbe2f3f2c3f7f3f0e,0x3f1dbe79bf6abf62,0x3f393f7d3efcbec4,0xbea1bf71bf58bdc9,0x3f7a3edbbee6bf7b,0xbf77bf4ebcc93f46,0x3eb8bf04bf7ebf35,0xbf423d493f513f75,
0x3f7c3f3ebd97bf55,0xbf4abf78becf3ef1,0x3f31be16bf5fbf6d,0xbf73beac3f093f7f,0xbe60bf67bf65be48,0xbe893f183f803f22,0xbf6fbf5cbdfb3f35,0x3f273f803f13be95,
0x3f623e48bf22bf80,0xbf7fbf0e3e953f6d,0x3f753f553dc9bf35,0xbf46bf7bbef13ec4,0x3ef13f7b3f460000,0xbdc9bf55bf75bec4,0xbe953f0e3f7f3f35,0x3f22be48bf62bf6d,
0xbef1bf7bbf468000,0x3dc93f553f753ec4,0x3e95bf0ebf7fbf35,0xbf223e483f623f6d,0x3f623e48bf22bf80,0xbf7fbf0e3e953f6d,0x3f753f553dc9bf35,0xbf46bf7bbef13ec4,
0x3f313f803f1dbe48,0xbee6bf78bf51bdc9,0x3f7a3f4e3d97bf35,0xbf5fbf71beb83ef1,0xbecf3edb3f773f55,0x3f27be16bf58bf75,0x3e2f3f5c3f733ec4,0x3dfbbf2cbf80bf22,
0x3f39bd49bf4abf7b,0xbf65be793f133f7f,0x3e60bf18bf7fbf35,0xbefc3eac3f6f3f62,0x3f6a3f673e89bf0e,0xbf42bf7dbf093e95,0x3f7c3f04bea1bf6d,0xbf7ebf3e3cc93f46,
0xbe163f223f803f35,0x3eacbef1bf78bf55,0xbf043e953f673f6d,0x3f2cbdc9bf4ebf7b,0x3f183f7f3f3e0000,0xbedbbf75bf5cbe48,0x3e793f623f713ec4,0xbd49bf46bf7dbf0e,
0x3f7d3f463d49bf35,0xbf71bf62be793f0e,0x3f5c3f753edbbec4,0xbf3ebf7fbf183e48,0x3f4e3dc9bf2cbf80,0xbf67be953f043f7b,0x3f783ef1beacbf6d,0xbf80bf223e163f55,
0xbf1d3e163f513f7b,0x3f31bd49bf42bf7f,0xbee63eac3f6a3f6d,0x3f09be79bf5fbf75,0xbe893f043f7a3f55,0x3eb8bedbbf73bf62,0xbd973f2c3f803f35,0x3e2fbf18bf7ebf46,
0x3f4a3f7d3f13be48,0xbf39bf80bf273dc9,0x3f653f713ecfbec4,0xbf58bf78befc3e95,0x3f773f5c3e60bf0e,0xbf6fbf67bea13ef1,0x3f7f3f3e3cc9bf35,0xbf7cbf4ebdfb3f22,
};
__device__ __align__(1024) uint8_t g_hT[32 * 262144];
__device__ __align__(1024) bf16 g_U[128 * 2 * 8 * 1024];
__device__ __align__(128) float2 g_gate[2048];
__device__ __align__(16) uint4 g_agg[16 * 512];
__device__ unsigned g_cnt[8 * 32];
constexpr int CNT_U = 0, CNT_V = 1, CNT_H = 2  , CNT_DONE = 4, CNT_EPOCH = 5;
#define PROFK(i) do { } while (0)
#define PROFC(i) do { } while (0)
#define PROF(i) do { } while (0)
#define PROFG(i) do { } while (0)

constexpr int SLOT = 32768;
constexpr int OFF_HS = 4 * SLOT;
constexpr int OFF_U = 5 * SLOT;
constexpr int OFF_W = OFF_U + 32768;
constexpr int OFF_F = OFF_W + 18432;
constexpr int OFF_D = OFF_F + 8192;
constexpr int OFF_GW = OFF_D + 4096;
constexpr int OFF_G = OFF_W + 32768;
constexpr int OFF_BAR = OFF_G + 1024;
constexpr int OFF_GS = OFF_BAR + 256;
constexpr int OFF_DUMMY = OFF_GS + 128;
constexpr int SMEM_BYTES = OFF_DUMMY + 16;
constexpr int BAR_FULL = 0  , BAR_X = 10, BAR_U = 11, BAR_W = 12, BAR_T = 13, BAR_F = 14  ,
              BAR_EMPTY = 17  , BAR_HW = 22  , BAR_WR = 26, BAR_VW = 27, BAR_S1 = 28,
              BAR_CD = 29, BAR_C = 30  , NBAR = 32;

#define DEVI __device__ __forceinline__
constexpr unsigned SPIN_LIMIT = 1u << 22;

DEVI uint32_t smem_u32(const void* p) { return (uint32_t)__cvta_generic_to_shared(p); }
DEVI uint64_t gtime() { uint64_t t; asm volatile("mov.u64 %0, %%globaltimer;" : "=l"(t)); return t; }
DEVI void mbar_init(uint32_t bar, uint32_t cnt) { asm volatile("mbarrier.init.shared::cta.b64 [%0], %1;" :: "r"(bar), "r"(cnt) : "memory"); }
DEVI void mbar_expect_tx(uint32_t bar, uint32_t bytes) { asm volatile("mbarrier.arrive.expect_tx.shared::cta.b64 _, [%0], %1;" :: "r"(bar), "r"(bytes) : "memory"); }
DEVI void mbar_arrive(uint32_t bar) { asm volatile("mbarrier.arrive.shared::cta.b64 _, [%0];" :: "r"(bar) : "memory"); }
DEVI void mbar_wait(uint32_t bar, uint32_t parity) {
    asm volatile("{\n.reg .pred p;\n.reg .u32 n;\nmov.u32 n, 0;\n"
                 "LW:\nmbarrier.try_wait.parity.shared::cta.b64 p, [%0], %1;\n@p bra LD;\n"
                 "add.u32 n, n, 1;\nsetp.lt.u32 p, n, %2;\n@p bra LW;\nLD:\n}"
                 :: "r"(bar), "r"(parity), "n"(1 << 17) : "memory");
}
DEVI bool elect() {
    uint32_t p;
    asm volatile("{\n.reg .pred P;\nelect.sync _|P, 0xffffffff;\nselp.u32 %0, 1, 0, P;\n}" : "=r"(p));
    return p;
}
DEVI void fence_barrier_init() { asm volatile("fence.mbarrier_init.release.cluster;" ::: "memory"); }
DEVI void fence_proxy_async_smem() { asm volatile("fence.proxy.async.shared::cta;" ::: "memory"); }
DEVI void helper_sync() { asm volatile("bar.sync 1, 128;" ::: "memory"); }

DEVI void wait_counter(const unsigned* p, unsigned target) {
    for (unsigned n = 0;; n++) {
        unsigned v;
        asm volatile("ld.relaxed.gpu.global.u32 %0, [%1];" : "=r"(v) : "l"(p) : "memory");
        if ((int)(v - target) >= 0 || n > SPIN_LIMIT) break;
    }
}
DEVI void signal_counter(unsigned* p) {
    asm volatile("red.relaxed.gpu.global.add.u32 [%0], 1;" :: "l"(p) : "memory");
}

DEVI void tma_load_3d(uint32_t dst, const CUtensorMap* map, uint32_t bar, int c0, int c1, int c2) {
    asm volatile("cp.async.bulk.tensor.3d.shared::cluster.global.mbarrier::complete_tx::bytes [%0], [%1, {%3, %4, %5}], [%2];"
        :: "r"(dst), "l"(map), "r"(bar), "r"(c0), "r"(c1), "r"(c2) : "memory");
}
DEVI void tma_load_4d(uint32_t dst, const CUtensorMap* map, uint32_t bar, int c0, int c1, int c2, int c3) {
    asm volatile("cp.async.bulk.tensor.4d.shared::cluster.global.mbarrier::complete_tx::bytes [%0], [%1, {%3, %4, %5, %6}], [%2];"
        :: "r"(dst), "l"(map), "r"(bar), "r"(c0), "r"(c1), "r"(c2), "r"(c3) : "memory");
}
DEVI void tma_store_5d(const CUtensorMap* map, uint32_t src, int c0, int c4) {
    asm volatile("cp.async.bulk.tensor.5d.global.shared::cta.bulk_group [%0, {%2, %4, %4, %4, %3}], [%1];"
        :: "l"(map), "r"(src), "r"(c0), "r"(c4), "r"(0) : "memory");
}
DEVI void tma_store_4d(const CUtensorMap* map, uint32_t src, int c0, int c1, int c2, int c3) {
    asm volatile("cp.async.bulk.tensor.4d.global.shared::cta.bulk_group [%0, {%2, %3, %4, %5}], [%1];"
        :: "l"(map), "r"(src), "r"(c0), "r"(c1), "r"(c2), "r"(c3) : "memory");
}
DEVI void bulk_load(uint32_t dst, const void* src, uint32_t bytes, uint32_t bar) {
    asm volatile("cp.async.bulk.shared::cluster.global.mbarrier::complete_tx::bytes [%0], [%1], %2, [%3];"
        :: "r"(dst), "l"(src), "r"(bytes), "r"(bar) : "memory");
}
DEVI void bulk_prefetch_l2(const void* src, uint32_t bytes) {
    asm volatile("cp.async.bulk.prefetch.L2.global [%0], %1;" :: "l"(src), "r"(bytes) : "memory");
}
DEVI void tma_store_3d(const CUtensorMap* map, uint32_t src, int c0, int c1, int c2) {
    asm volatile("cp.async.bulk.tensor.3d.global.shared::cta.bulk_group [%0, {%2, %3, %4}], [%1];"
        :: "l"(map), "r"(src), "r"(c0), "r"(c1), "r"(c2) : "memory");
}
DEVI void pause(unsigned n) {
    asm volatile("{\n.reg .pred p;\n.reg .u32 a, b;\nmov.u32 a, %%clock;\n"
                 "LP:\nmov.u32 b, %%clock;\nsub.u32 b, b, a;\nsetp.lt.u32 p, b, %0;\n@p bra LP;\n}" :: "r"(n) : "memory");
}
DEVI void bulk_store(void* dst, uint32_t src, uint32_t bytes) {
    asm volatile("cp.async.bulk.global.shared::cta.bulk_group [%0], [%1], %2;" :: "l"(dst), "r"(src), "r"(bytes) : "memory");
}
DEVI void bulk_commit() { asm volatile("cp.async.bulk.commit_group;" ::: "memory"); }
DEVI void bulk_wait0() { asm volatile("cp.async.bulk.wait_group 0;" ::: "memory"); }

DEVI void wgmma_fence() { asm volatile("wgmma.fence.sync.aligned;" ::: "memory"); }
DEVI void wgmma_commit() { asm volatile("wgmma.commit_group.sync.aligned;" ::: "memory"); }
template<int N> DEVI void wgmma_wait() { asm volatile("wgmma.wait_group.sync.aligned %0;" :: "n"(N) : "memory"); }
template<int N> DEVI void wgmma_wait_all(float (&d)[N]) {
    wgmma_wait<0>();
#pragma unroll
    for (int i = 0; i < N; i++) asm volatile("" : "+f"(d[i]) :: "memory");
}
template<int R> DEVI void reg_alloc() { asm volatile("setmaxnreg.inc.sync.aligned.u32 %0;" :: "n"(R)); }
template<int R> DEVI void reg_dealloc() { asm volatile("setmaxnreg.dec.sync.aligned.u32 %0;" :: "n"(R)); }

DEVI uint64_t make_desc(uint32_t addr, uint32_t lbo, uint32_t sbo, uint32_t mode = 1) {
    return (uint64_t)(((addr & 0x3FFFF) >> 4) | ((lbo >> 4) << 16)) | ((uint64_t)((sbo >> 4) | (mode << 30)) << 32);
}

#define ACC8(a, o) "+f"(a[o+0]), "+f"(a[o+1]), "+f"(a[o+2]), "+f"(a[o+3]), "+f"(a[o+4]), "+f"(a[o+5]), "+f"(a[o+6]), "+f"(a[o+7])
#define OUT8(a, o) "=f"(a[o+0]), "=f"(a[o+1]), "=f"(a[o+2]), "=f"(a[o+3]), "=f"(a[o+4]), "=f"(a[o+5]), "=f"(a[o+6]), "=f"(a[o+7])
#define ACC32(a, o) ACC8(a, o), ACC8(a, o+8), ACC8(a, o+16), ACC8(a, o+24)

template<int TA, int TB>
DEVI void wgmma_n128(float (&d)[64], uint64_t da, uint64_t db, int scale_d) {
    asm volatile("{\n.reg .pred p;\nsetp.ne.b32 p, %66, 0;\n"
        "wgmma.mma_async.sync.aligned.m64n128k16.f32.bf16.bf16 "
        "{%0, %1, %2, %3, %4, %5, %6, %7, %8, %9, %10, %11, %12, %13, %14, %15, "
        "%16, %17, %18, %19, %20, %21, %22, %23, %24, %25, %26, %27, %28, %29, %30, %31, "
        "%32, %33, %34, %35, %36, %37, %38, %39, %40, %41, %42, %43, %44, %45, %46, %47, "
        "%48, %49, %50, %51, %52, %53, %54, %55, %56, %57, %58, %59, %60, %61, %62, %63}, "
        "%64, %65, p, 1, 1, %67, %68;\n}\n"
        : ACC32(d, 0), ACC32(d, 32)
        : "l"(da), "l"(db), "r"(scale_d), "n"(TA), "n"(TB));
}
#define SS_N16 "{\n.reg .pred p;\nsetp.ne.b32 p, 0, 0;\n" \
        "wgmma.mma_async.sync.aligned.m64n16k16.f32.bf16.bf16 " \
        "{%0, %1, %2, %3, %4, %5, %6, %7}, %8, %9, p, 1, 1, %10, 0;\n}\n"
template<int TA> DEVI void wgmma_n16(float* d, uint64_t da, uint64_t db) {
    asm volatile(SS_N16 : OUT8(d, 0) : "l"(da), "l"(db), "n"(TA));
}
#define RS_N64 "{\n.reg .pred p;\nsetp.ne.b32 p, %37, 0;\n" \
        "wgmma.mma_async.sync.aligned.m64n64k16.f32.bf16.bf16 " \
        "{%0, %1, %2, %3, %4, %5, %6, %7, %8, %9, %10, %11, %12, %13, %14, %15, " \
        "%16, %17, %18, %19, %20, %21, %22, %23, %24, %25, %26, %27, %28, %29, %30, %31}, " \
        "{%32, %33, %34, %35}, %36, p, 1, 1, %38;\n}\n"
template<int SCALE_D, int TB = 0>
DEVI void wgmma_rs_n64(float (&d)[32], const uint32_t (&a)[4], uint64_t db) {
    if (SCALE_D) asm volatile(RS_N64 : ACC32(d, 0) : "r"(a[0]), "r"(a[1]), "r"(a[2]), "r"(a[3]), "l"(db), "n"(1), "n"(TB));
    else asm volatile(RS_N64 : OUT8(d, 0), OUT8(d, 8), OUT8(d, 16), OUT8(d, 24) : "r"(a[0]), "r"(a[1]), "r"(a[2]), "r"(a[3]), "l"(db), "n"(0), "n"(TB));
}
DEVI void ldsm_x4_t(uint32_t (&r)[4], uint32_t addr) {
    asm volatile("ldmatrix.sync.aligned.m8n8.x4.trans.shared.b16 {%0, %1, %2, %3}, [%4];"
        : "=r"(r[0]), "=r"(r[1]), "=r"(r[2]), "=r"(r[3]) : "r"(addr) : "memory");
}
DEVI void ldsm_x4(uint32_t (&r)[4], uint32_t addr) {
    asm volatile("ldmatrix.sync.aligned.m8n8.x4.shared.b16 {%0, %1, %2, %3}, [%4];"
        : "=r"(r[0]), "=r"(r[1]), "=r"(r[2]), "=r"(r[3]) : "r"(addr) : "memory");
}
DEVI void stsm_x4(uint32_t addr, uint32_t r0, uint32_t r1, uint32_t r2, uint32_t r3) {
    asm volatile("stmatrix.sync.aligned.m8n8.x4.shared.b16 [%0], {%1, %2, %3, %4};"
        :: "r"(addr), "r"(r0), "r"(r1), "r"(r2), "r"(r3) : "memory");
}
DEVI void stsm_x4_t(uint32_t addr, uint32_t r0, uint32_t r1, uint32_t r2, uint32_t r3) {
    asm volatile("stmatrix.sync.aligned.m8n8.x4.trans.shared.b16 [%0], {%1, %2, %3, %4};"
        :: "r"(addr), "r"(r0), "r"(r1), "r"(r2), "r"(r3) : "memory");
}
DEVI uint32_t movm(uint32_t a) { uint32_t d; asm volatile("movmatrix.sync.aligned.m8n8.trans.b16 %0, %1;" : "=r"(d) : "r"(a)); return d; }
DEVI uint32_t pack2(float lo, float hi) { uint32_t d; asm("cvt.rn.bf16x2.f32 %0, %1, %2;" : "=r"(d) : "f"(hi), "f"(lo)); return d; }
DEVI float bf_lo(uint32_t v) { return __uint_as_float(v << 16); }
DEVI float bf_hi(uint32_t v) { return __uint_as_float(v & 0xffff0000u); }
DEVI float bf_round(float v) { return __bfloat162float(__float2bfloat16_rn(v)); }
DEVI uint32_t bf_mul2(uint32_t a, uint32_t b) { uint32_t d; asm("mul.rn.bf16x2 %0, %1, %2;" : "=r"(d) : "r"(a), "r"(b)); return d; }
DEVI uint32_t bf_add2(uint32_t a, uint32_t b) { uint32_t d; asm("add.rn.bf16x2 %0, %1, %2;" : "=r"(d) : "r"(a), "r"(b)); return d; }
DEVI uint32_t bf_sub2(uint32_t a, uint32_t b) { uint32_t d; asm("sub.rn.bf16x2 %0, %1, %2;" : "=r"(d) : "r"(a), "r"(b)); return d; }
DEVI uint4 lds128u(uint32_t a) { uint4 v; asm volatile("ld.shared.v4.u32 {%0, %1, %2, %3}, [%4];" : "=r"(v.x), "=r"(v.y), "=r"(v.z), "=r"(v.w) : "r"(a) : "memory"); return v; }
DEVI void sts128u(uint32_t a, uint32_t x, uint32_t y, uint32_t z, uint32_t w) { asm volatile("st.shared.v4.u32 [%0], {%1, %2, %3, %4};" :: "r"(a), "r"(x), "r"(y), "r"(z), "r"(w) : "memory"); }
DEVI uint2 lds64u(uint32_t a) { uint2 v; asm volatile("ld.shared.v2.u32 {%0, %1}, [%2];" : "=r"(v.x), "=r"(v.y) : "r"(a) : "memory"); return v; }
DEVI uint32_t ldg32u(const void* p) { uint32_t v; asm volatile("ld.global.nc.u32 %0, [%1];" : "=r"(v) : "l"(p) : "memory"); return v; }
DEVI void sts64(uint32_t a, float x, float y) { asm volatile("st.shared.v2.f32 [%0], {%1, %2};" :: "r"(a), "f"(x), "f"(y) : "memory"); }
DEVI void sts32(uint32_t a, uint32_t v) { asm volatile("st.shared.u32 [%0], %1;" :: "r"(a), "r"(v) : "memory"); }
DEVI uint32_t lds16(uint32_t a) { uint32_t v; asm volatile("ld.shared.u16 %0, [%1];" : "=r"(v) : "r"(a) : "memory"); return v; }
DEVI void cmul2(uint32_t& x, uint32_t& y, uint32_t c, uint32_t s) {
    asm("{\n.reg .b32 t, u;\nxor.b32 t, %3, 0x80008000;\nmul.rn.bf16x2 t, %1, t;\nmul.rn.bf16x2 u, %1, %2;\n"
        "fma.rn.bf16x2 %1, %0, %3, u;\nfma.rn.bf16x2 %0, %0, %2, t;\n}" : "+r"(x), "+r"(y) : "r"(c), "r"(s));
}
DEVI void sts16(uint32_t a, float v) { asm volatile("st.shared.u16 [%0], %1;" :: "r"(a), "r"(pack2(v, v)) : "memory"); }

DEVI float2 cmul(float2 a, float2 b) { return make_float2(fmaf(a.x, b.x, -a.y * b.y), fmaf(a.x, b.y, a.y * b.x)); }
DEVI float2 cfma(float2 a, float2 b, float2 c) { return make_float2(fmaf(a.x, b.x, fmaf(-a.y, b.y, c.x)), fmaf(a.x, b.y, fmaf(a.y, b.x, c.y))); }

struct Params {
    const bf16 *lam_re, *lam_im, *log_dt, *dskip, *gate_w, *c_re, *c_im, *b_re, *b_im;
    int swapB, ones;
    uint8_t perm[68];
};

DEVI void radix8(uint32_t sb, uint32_t gtab, int w, int lane, int bar) {
    const uint64_t dg = make_desc(gtab, 128, 256, 0);
    const uint32_t st = sb + OFF_U + (lane >> 4) * 16384 + (lane & 7) * 128 + (((2 * w + ((lane >> 3) & 1)) ^ (lane & 7)) << 4);
    float acc[16][8];
    const uint64_t da = make_desc(sb + OFF_U, 16, 16384);
    wgmma_fence();
#pragma unroll
    for (int i = 0; i < 16; i++) wgmma_n16<1>(acc[i], da + 64 * i, dg);
    wgmma_commit();
    wgmma_wait<0>();
    asm volatile("bar.sync %0, 128;" :: "r"(bar) : "memory");
#pragma unroll
    for (int i = 0; i < 16; i++)
        stsm_x4_t((st ^ ((i & 3) << 4)) + i * 1024,
                  pack2(acc[i][0], acc[i][1]), pack2(acc[i][2], acc[i][3]), pack2(acc[i][4], acc[i][5]), pack2(acc[i][6], acc[i][7]));
}

template<int N> DEVI void c_take(float (&acc)[32], uint32_t (&p)[16]) {
    wgmma_wait<N>();
#pragma unroll
    for (int i = 0; i < 32; i++) asm volatile("" : "+f"(acc[i]) :: "memory");
#pragma unroll
    for (int i = 0; i < 16; i++) p[i] = pack2(acc[2 * i], acc[2 * i + 1]);
}
DEVI void c_mm4(float (&acc)[32], const uint32_t (&a)[4][4], uint64_t df) {
    wgmma_rs_n64<0>(acc, a[0], df);
    wgmma_rs_n64<1>(acc, a[1], df + 2);
    wgmma_rs_n64<1>(acc, a[2], df + 4);
    wgmma_rs_n64<1>(acc, a[3], df + 6);
    wgmma_commit();
}
template<int H> DEVI void c_mm2(float (&acc)[2][32], const uint32_t (&a)[2][2][4], uint64_t df) {
    wgmma_fence();
#pragma unroll
    for (int i = 0; i < 2; i++) {
        wgmma_rs_n64<H>(acc[i], a[i][0], df + 2 * H);
        wgmma_rs_n64<1>(acc[i], a[i][1], df + 2 * H + 4);
        wgmma_commit();
    }
}
DEVI void c_twiddle(uint32_t (&p)[16], uint32_t (&a)[2][2][4], const uint4* tw) {
#pragma unroll
    for (int jp = 0; jp < 2; jp++)
#pragma unroll
        for (int hh = 0; hh < 2; hh++) {
            const uint4 w = tw[hh * 2 + jp];
#pragma unroll
            for (int jl = 0; jl < 2; jl++) {
                const int o = 4 * jp + 2 * jl + hh;
                cmul2(p[o], p[8 + o], jl ? w.z : w.x, jl ? w.w : w.y);
                a[jp][0][2 * hh + jl] = movm(p[o]);
                a[jp][1][2 * hh + jl] = movm(p[8 + o]);
            }
        }
}
template<bool LW> DEVI void c_stage(float (&acc)[2][32], const uint4 (&tw)[8], uint64_t df, uint32_t (&w)[2][4][4], uint32_t wa, uint32_t wm) {
    uint32_t p[16], a0[2][2][4], a1[2][2][4];
    c_take<1>(acc[0], p);
    c_twiddle(p, a0, tw);
    c_take<0>(acc[1], p);
    if (LW) {
#pragma unroll
        for (int j = 0; j < 4; j++) ldsm_x4_t(w[0][j], (j < 2 ? wa : wm) + (j & 1) * 512);
    }
    c_mm2<0>(acc, a0, df);
    c_twiddle(p, a1, tw + 4);
    if (LW) {
#pragma unroll
        for (int j = 0; j < 4; j++) ldsm_x4_t(w[1][j], ((j < 2 ? wa : wm) ^ 32) + (j & 1) * 512);
    }
    c_mm2<1>(acc, a1, df);
}

DEVI void phase_c(uint32_t sb, int warp, int mrow, int lane, const uint4 (&tw)[8]) {
    PROFC(0);
    const uint64_t df = make_desc(sb + OFF_F, 16, 1024);
    float acc[2][32];
    uint32_t w[2][4][4];
    const uint32_t xa = sb + OFF_U + ((lane >> 4) * 4 + ((lane & 7) >> 1)) * 1024 + warp * 128
                      + ((((lane & 1) * 4 + ((lane >> 3) & 1)) ^ warp ^ ((lane >> 1) & 3)) << 4);
    const uint32_t wo = sb + OFF_W + (lane >> 4) * 9216 + (lane & 7) * 64 + ((((lane >> 3) & 1) ^ ((lane >> 1) & 3)) << 4);
    const uint32_t wa = wo + (warp >> 1) * 1152, wm = wo + 4608 + mrow * 1152;
    {
        uint32_t a[2][4][4];
#pragma unroll
        for (int h = 0; h < 2; h++)
#pragma unroll
            for (int s = 0; s < 4; s++) ldsm_x4_t(a[h][s], (xa ^ (h * 32)) + (s & 1) * 8192 + (s >> 1) * 16384);
        wgmma_fence();
        c_mm4(acc[0], a[0], df);
        c_mm4(acc[1], a[1], df);
    }
    PROFC(1);
    c_stage<true>(acc, tw, df, w, wa, wm);
    PROFC(2);
#pragma unroll
    for (int h = 0; h < 2; h++) {
        uint32_t p[16], a[4][4];
        c_take<1>(acc[h], p);
#pragma unroll
        for (int j = 0; j < 4; j++)
#pragma unroll
            for (int hh = 0; hh < 2; hh++) {
                cmul2(p[2 * j + hh], p[8 + 2 * j + hh], w[h][j][hh], w[h][j][2 + hh]);
                a[j >> 1][2 * (j & 1) + hh] = p[8 + 2 * j + hh];
                a[2 + (j >> 1)][2 * (j & 1) + hh] = p[2 * j + hh];
            }
        wgmma_fence();
        c_mm4(acc[h], a, df);
    }
    __syncwarp();
    if (lane == 0) mbar_arrive(sb + OFF_BAR + 8 * BAR_WR);
    PROFC(3);
    c_stage<false>(acc, tw, df, w, wa, wm);
    PROFC(4);
#pragma unroll
    for (int h = 0; h < 2; h++) {
        uint32_t p[16];
        if (h) c_take<0>(acc[1], p); else c_take<1>(acc[0], p);
#pragma unroll
        for (int s = 0; s < 4; s++)
            stsm_x4_t((xa ^ (h * 32)) + (s & 1) * 8192 + ((s >> 1) ^ 1) * 16384, p[4 * s], p[4 * s + 1], p[4 * s + 2], p[4 * s + 3]);
    }
    PROFC(5);
}

#define PACE_V 250
#define VPOS 28
#define C0 1
#define NS 4
#define PACE_H 200
#define T_W0 1500
#define PF_BA 1500
#define XT0 4
#define POL1 0
#define POL2 1
#define T_B2 4000
#define T_W 7500
#define PACE_U 400
#define PACE_L 300
#define T_C 3000
DEVI void tma_prefetch_4d(const CUtensorMap* map, int c0, int c1, int c2, int c3) {
    asm volatile("cp.async.bulk.prefetch.tensor.4d.L2.global [%0, {%1, %2, %3, %4}];" :: "l"(map), "r"(c0), "r"(c1), "r"(c2), "r"(c3) : "memory");
}
DEVI void bar_sync(int id, int n) { asm volatile("bar.sync %0, %1;" :: "r"(id), "r"(n) : "memory"); }
DEVI void bar_arrive(int id, int n) { asm volatile("bar.arrive %0, %1;" :: "r"(id), "r"(n) : "memory"); }
DEVI void stg128(void* p, uint32_t x, uint32_t y, uint32_t z, uint32_t w) { asm volatile("st.global.v4.u32 [%0], {%1, %2, %3, %4};" :: "l"(p), "r"(x), "r"(y), "r"(z), "r"(w) : "memory"); }
DEVI uint4 ldg128(const void* p) { uint4 v; asm volatile("ld.global.nc.v4.u32 {%0, %1, %2, %3}, [%4];" : "=r"(v.x), "=r"(v.y), "=r"(v.z), "=r"(v.w) : "l"(p)); return v; }
DEVI uint32_t ldg16(const void* p) { uint32_t v; asm volatile("ld.global.nc.u16 %0, [%1];" : "=r"(v) : "l"(p)); return v; }
DEVI float2 lds64f(uint32_t a) { float2 v; asm volatile("ld.shared.v2.f32 {%0, %1}, [%2];" : "=f"(v.x), "=f"(v.y) : "r"(a) : "memory"); return v; }

__global__ void __cluster_dims__(2, 1, 1) __launch_bounds__(384, 1)
fused_kernel(const __grid_constant__ CUtensorMap mapB, const __grid_constant__ CUtensorMap mapX,
             const __grid_constant__ CUtensorMap mapXs, const __grid_constant__ CUtensorMap mapU0,
             const __grid_constant__ CUtensorMap mapU2, const __grid_constant__ CUtensorMap mapXe,
             const __grid_constant__ CUtensorMap mapCre, const __grid_constant__ CUtensorMap mapCim,
             const __grid_constant__ CUtensorMap mapV, const __grid_constant__ CUtensorMap mapO,
             const __grid_constant__ CUtensorMap mapWr, const __grid_constant__ CUtensorMap mapWi,
             const __grid_constant__ CUtensorMap mapH,
             const __grid_constant__ Params P) {
    extern __shared__ __align__(1024) uint8_t sm[];
    const uint32_t sb = smem_u32(sm);
    const uint32_t bars = sb + OFF_BAR;
    const int b = P.perm[blockIdx.x >> 1] * 2 + (blockIdx.x & 1), tid = threadIdx.x, warp = __shfl_sync(0xffffffffu, tid >> 5, 0), lane = tid & 31;
    const bool main_cta = b < 128;
    if (b == 129) return;
    const int rp = (b >> 1) & 3, mq = ((b >> 3) & 2) + (b & 1), dt = ((b >> 1) & 4) + (b >> 5), tc = 4 * rp + mq;
    const int cls = b == 128 ? 128 : (b & 31) ? (b & 31) + 64 * (b >> 5) : (b == 64 ? 32 : b == 32 ? 64 : b);
    auto load_g1 = [&](int k, int s) {
        const uint32_t full = bars + 8 * (BAR_FULL + s + (k >> 4) * 5), st = sb + s * SLOT;
        mbar_expect_tx(full, k ? SLOT : SLOT + 2048);
        tma_load_4d(st, &mapB, full, (k & 15) * 64, 0, 0, dt * 8 + (k >> 4) * 64);
        tma_load_4d(st + 16384, &mapX, full, (k & 15) * 64, 0, 0, tc * 64);
    };
    auto load_xs = [&](int k) {
        if ((unsigned)(k - XT0) < 4) {
            if (k == XT0) mbar_expect_tx(bars + 8 * BAR_X, 32768);
            tma_load_4d(sb + OFF_U + (k - XT0) * 8192, &mapXs, bars + 8 * BAR_X, (b & 15) * 64, 0, k - XT0, b >> 4);
        }
    };
    if (elect()) {
        asm volatile("prefetch.tensormap [%0];" :: "l"(&mapB + warp) : "memory");
        if (warp == 11) PROFG(0);
    }
    const bool real_cls = (cls & 127) == 0;
    const int t = tid & 127;
    auto load_epoch = [&]() {
        unsigned e;
        asm volatile("ld.relaxed.gpu.global.u32 %0, [%1];" : "=r"(e) : "l"(&g_cnt[CNT_EPOCH * 32]));
        return e + 1;
    };
    const int g = lane >> 2, q = lane & 3;

    if (warp < 8) {
        reg_alloc<216>();
        uint32_t fa[16][4], lr_, li_, ld_, dk_;
        if ((warp >> 2) == 1) {
            const int pp = (dt * 64 + (t & 63) + (t & 64) * 8) & 1023;
            lr_ = ldg16(P.lam_re + pp); li_ = ldg16(P.lam_im + pp); ld_ = ldg16(P.log_dt + pp); dk_ = ldg16(P.dskip + ((dt * 128 + t) & 1023));
#pragma unroll
            for (int i = 0; i < 16; i++) {
                const uint4 v = ldg128((const uint4*)c_tab + i * 128 + t);
                fa[i][0] = v.x; fa[i][1] = v.y; fa[i][2] = v.z; fa[i][3] = v.w;
            }
            const int kk = (t >> 3) & 7, r = t & 7;
            float sn, cs;
            sincospif((float)(((cls + 256 * kk) * r) & 2047) * (1.f / 1024.f), &sn, &cs);
            sn *= 1.f / 1024.f; cs *= 1.f / 1024.f;
            const uint32_t gf = sb + OFF_G + kk * 16 + r * 2, gi = sb + OFF_G + 512 + r * 16 + kk * 2;
            if (t < 64) {
                sts16(gf, cs); sts16(gf + 128, real_cls ? 0.f : sn); sts16(gf + 256, -sn); sts16(gf + 384, real_cls ? 0.f : cs);
                sts16(gi, cs); sts16(gi + 128, -sn); sts16(gi + 256, sn); sts16(gi + 384, cs);
            }
        }
        bar_sync(0, 384);
        if (tid == 0) PROF(28);
        if (tid == 224) PROFG(8);
        const int wg = warp >> 2, w = warp & 3;
        const unsigned epoch = load_epoch();
        const uint32_t fb = bars + 8 * (BAR_FULL + 5 * wg);
        uint32_t phm = 0;
        if (wg) {
            if (main_cta) {
                {
                    const float lr = bf_lo(lr_), li = bf_lo(li_);
                    const float dl = bf_round(expf(bf_lo(ld_)));
                    const float mag = expf(dl * lr);
                    float sn, cs; sincospif(dl * li * 0.31830988618379067f, &sn, &cs);
                    float2 l1 = make_float2(mag * cs, mag * sn);
                    const float inv = 1.f / (lr * lr + li * li);
                    const float2 cf = cmul(make_float2(l1.x - 1.f, l1.y), make_float2(lr * inv, -li * inv));
                    if (P.swapB) l1.y = -l1.y;
                    float2 z = cmul(l1, l1);
                    z = cmul(z, z);
                    const float2 l8 = cmul(z, z);
                    z = cmul(l8, l8);
                    const float2 l32 = cmul(z, z), l64 = cmul(l32, l32), l128 = cmul(l64, l64), l256 = cmul(l128, l128);
                    const float2 one = make_float2(1.f, 0.f);
                    auto put = [&](uint32_t a, float2 u, float2 v) { sts128u(sb + OFF_HS + a, __float_as_uint(u.x), __float_as_uint(u.y), __float_as_uint(v.x), __float_as_uint(v.y)); };
                    put(t * 16, l1, cf); put(2048 + t * 16, l32, l64); put(4096 + t * 16, cmul(l256, l256), l8);
                    put(6144 + t * 64, one, one); put(6160 + t * 64, l128, l32); put(6176 + t * 64, l256, l64); put(6192 + t * 64, cmul(l128, l256), cmul(l32, l64));
                    const uint32_t dv = dk_ << ((t & 1) * 16), dq = (t >> 1) & 3;
                    const uint32_t da = sb + OFF_D + (t >> 3) * 256 + (t & 7) * 16;
                    sts128u(da, dq == 0 ? dv : 0u, dq == 1 ? dv : 0u, dq == 2 ? dv : 0u, dq == 3 ? dv : 0u);
                    sts128u(da + 128, 0u, 0u, 0u, 0u);
                }
                const uint32_t ua = sb + OFF_U + (lane >> 4) * 4096 + (8 * w + (lane & 7)) * 128 + ((((lane >> 3) & 1) ^ (lane & 7)) << 4);
                float acc[4][32];
                const uint64_t db = make_desc(sb + OFF_U, 8192, 1024);
                mbar_wait(bars + 8 * BAR_X, 0);
                if (t == 0) PROF(8);
                uint32_t x[4][8], y[4][8];
#pragma unroll
                for (int m = 0; m < 6; m++) {
                    if (m >= 2) {
                        const int n = m - 2;
                        if (m < 5) wgmma_wait<1>(); else wgmma_wait<0>();
#pragma unroll
                        for (int i = 0; i < 32; i++) asm volatile("" : "+f"(acc[n][i]) :: "memory");
#pragma unroll
                        for (int j = 0; j < 8; j++) { x[n][j] = pack2(acc[n][4 * j], acc[n][4 * j + 1]); y[n][j] = pack2(acc[n][4 * j + 2], acc[n][4 * j + 3]); }
                    }
                    if (m < 4) {
                        wgmma_fence();
                        wgmma_rs_n64<0, 1>(acc[m], fa[4 * m], db + 512 * m);
#pragma unroll
                        for (int j = 1; j < 4; j++) wgmma_rs_n64<1, 1>(acc[m], fa[4 * m + j], db + 512 * m + 128 * j);
                        wgmma_commit();
                    }
                }
                if (t < 4) {
#pragma unroll
                    for (int j = 0; j < 8; j++) {
                        const uint32_t s0 = bf_add2(x[0][j], x[2][j]), s2 = bf_add2(x[1][j], x[3][j]), ty = bf_sub2(y[1][j], y[3][j]), sy = bf_add2(y[1][j], y[3][j]);
                        const uint32_t b0 = y[0][j], b2 = y[2][j];
                        y[1][j] = bf_sub2(x[3][j], x[1][j]); x[1][j] = bf_sub2(x[0][j], x[2][j]);
                        x[0][j] = bf_add2(s0, s2); y[0][j] = bf_sub2(s0, s2);
                        x[2][j] = bf_add2(b0, ty); y[2][j] = bf_add2(sy, b2) ^ 0x80008000u;
                        x[3][j] = bf_sub2(b0, ty); y[3][j] = bf_sub2(b2, sy);
                    }
                } else {
#pragma unroll
                    for (int j = 0; j < 8; j++) {
                        const uint32_t s0x = bf_add2(x[0][j], x[2][j]), s1x = bf_sub2(x[0][j], x[2][j]), s2x = bf_add2(x[1][j], x[3][j]), tx = bf_sub2(x[1][j], x[3][j]);
                        const uint32_t s0y = bf_add2(y[0][j], y[2][j]), s1y = bf_sub2(y[0][j], y[2][j]), s2y = bf_add2(y[1][j], y[3][j]), ty = bf_sub2(y[1][j], y[3][j]);
                        x[0][j] = bf_add2(s0x, s2x); y[0][j] = bf_add2(s0y, s2y);
                        x[1][j] = bf_add2(s1x, ty); y[1][j] = bf_sub2(s1y, tx);
                        x[2][j] = bf_sub2(s0x, s2x); y[2][j] = bf_sub2(s0y, s2y);
                        x[3][j] = bf_sub2(s1x, ty); y[3][j] = bf_add2(s1y, tx);
                    }
                }
                helper_sync();
#pragma unroll
                for (int c = 0; c < 4; c++)
#pragma unroll
                    for (int j = 0; j < 8; j += 2) stsm_x4((ua ^ (j << 4)) + c * 8192, x[c][j], x[c][j + 1], y[c][j], y[c][j + 1]);
                if (t == 0) PROF(21);
            }
            fence_proxy_async_smem();
            __syncwarp();
            if (lane == 0) mbar_arrive(bars + 8 * BAR_S1);
        }
        uint4 tw[8];
        auto load_tw = [&]() {
#pragma unroll
            for (int i = 0; i < 8; i++) tw[i] = ldg128((const uint4*)(c_tab + 10240) + lane + i * 32);
        };
        if (main_cta) {
            float acc[2][64];
            const int gn = 16 * dt + 2 * warp + (lane >> 4);
            const uint32_t goff = 16384 + gn * 128 + ((((lane & 15) >> 1) ^ (gn & 7)) << 4) + (lane & 1) * 8;
            float gs = 0.f;
            float2 lam1[2], lam8[2], lam32[2], lam64[2], wq[2], w4[2], l32q[2], coef[2];
            auto get_consts = [&]() {
#pragma unroll
                for (int i = 0; i < 2; i++) {
                    auto get = [&](uint32_t a, float2& u, float2& v) {
                        const uint4 r = lds128u(sb + OFF_HS + a);
                        u = make_float2(__uint_as_float(r.x), __uint_as_float(r.y)); v = make_float2(__uint_as_float(r.z), __uint_as_float(r.w));
                    };
                    const uint32_t a = (64 * wg + 32 * i + (t >> 2)) * 16;
                    get(a, lam1[i], coef[i]); get(2048 + a, lam32[i], lam64[i]); get(4096 + a, w4[i], lam8[i]); get(6144 + 4 * a + q * 16, wq[i], l32q[i]);
                }
            };
            if (wg) {
                get_consts();
                asm volatile("st.volatile.shared.f32 [%0], %1;" :: "r"(sb + OFF_DUMMY), "f"(l32q[1].x) : "memory");
                bar_arrive(6, 256);
            }
            int s = wg * (16 % NS), sp = 0;
            if (wg) bar_sync(2, 256);
#pragma unroll 1
            for (int it = 0; it < 16; it++) {
                mbar_wait(fb + 8 * s, (phm >> s) & 1);
                phm ^= 1u << s;
                PROFK(16 * wg + it);
                const uint32_t st = sb + s * SLOT;
                const uint64_t da = make_desc(st, 16, 1024), db = make_desc(st + 16384, 16, 1024);
                uint2 xv = lds64u(st + goff);
                const uint2 gw = lds64u(sb + OFF_GW + (lane & 15) * 8 + it * 128);
                wgmma_fence();
#pragma unroll
                for (int j = 0; j < 4; j++) {
                    wgmma_n128<0, 0>(acc[0], da + 2 * j, db + 2 * j, (it | j) != 0);
                    wgmma_n128<0, 0>(acc[1], da + 512 + 2 * j, db + 2 * j, (it | j) != 0);
                }
                wgmma_commit();
                if (it == 15) bar_arrive(2 + wg, 256);
                xv.x = bf_mul2(xv.x, gw.x); xv.y = bf_mul2(xv.y, gw.y);
                gs += (bf_lo(xv.x) + bf_hi(xv.x)) + (bf_lo(xv.y) + bf_hi(xv.y));
                wgmma_wait<1>();
                if (it > 0 && lane == 0) mbar_arrive(bars + 8 * (BAR_EMPTY + sp));
                __syncwarp();
                sp = s;
                if (++s == NS) s = 0;
            }
            if (!wg) {
                bar_sync(6, 256);
                get_consts();
            }
#pragma unroll
            for (int o = 1; o < 16; o <<= 1) gs += __shfl_xor_sync(0xffffffffu, gs, o);
            {
                const float gg = bf_round(__fdividef(1.f, 1.f + __expf(-bf_round(gs))));
                if ((lane & 15) == 0) sts64(sb + OFF_GS + (2 * warp + (lane >> 4)) * 8, gg, bf_round(1.f - gg));
            }
            const uint4* ap = &g_agg[(tc - 1 - q) * 512 + (dt + 8 * wg) * 32 + (t >> 2)];
            const uint32_t tag = epoch & 15;
            wgmma_wait_all(acc[0]);
#pragma unroll
            for (int o = 0; o < 64; o++) asm volatile("" : "+f"(acc[1][o]) :: "memory");
            if (lane == 0) mbar_arrive(bars + 8 * (BAR_EMPTY + sp));
            if (tid == 0) PROF(3);
            if (tid == 128) PROF(25);
            if (tid == 224) PROFG(12);
            float2 ag[2][4], v[2];
#pragma unroll
            for (int c = 0; c < 8; c++) ag[c >> 2][c & 3] = make_float2(acc[c >> 2][16 * (c & 3)], acc[c >> 2][16 * (c & 3) + 2]);
#pragma unroll
            for (int r = 1; r < 8; r++)
#pragma unroll
                for (int c = 0; c < 8; c++) {
                    const int i = c >> 2, o = 16 * (c & 3) + 4 * (r >> 1) + (r & 1);
                    ag[i][c & 3] = cfma(lam1[i], ag[i][c & 3], make_float2(acc[i][o], acc[i][o + 2]));
                }
#pragma unroll
            for (int i = 0; i < 2; i++) {
                v[i] = ag[i][0];
#pragma unroll
                for (int c = 1; c < 4; c++) v[i] = cfma(lam8[i], v[i], ag[i][c]);
                float2 n = make_float2(__shfl_up_sync(0xffffffffu, v[i].x, 1, 4), __shfl_up_sync(0xffffffffu, v[i].y, 1, 4));
                if (q >= 1) v[i] = cfma(lam32[i], n, v[i]);
                n = make_float2(__shfl_up_sync(0xffffffffu, v[i].x, 2, 4), __shfl_up_sync(0xffffffffu, v[i].y, 2, 4));
                if (q >= 2) v[i] = cfma(lam64[i], n, v[i]);
            }
            if (q == 3 && tc < 15) {
                asm volatile("{\n.reg .b64 a, b;\nmov.b64 a, {%1, %2};\nmov.b64 b, {%3, %4};\nst.relaxed.gpu.global.v2.b64 [%0], {a, b};\n}"
                    :: "l"(ap + 2048), "r"((__float_as_uint(v[0].x) & ~15u) | tag), "r"(__float_as_uint(v[0].y)),
                       "r"((__float_as_uint(v[1].x) & ~15u) | tag), "r"(__float_as_uint(v[1].y)) : "memory");
            }
            uint4 rr[4];
#pragma unroll
            for (int n = 0; n < 4; n++) rr[n] = make_uint4(tag, 0u, tag, 0u);
            auto poll = [&]() {
#pragma unroll
                for (int n = 0; n < 4; n++)
                    asm volatile("{\n.reg .b64 a, b;\n.reg .pred p;\nsetp.lt.s32 p, %5, %6;\nmov.b64 a, {%0, %1};\nmov.b64 b, {%2, %3};\n"
                                 "@p ld.relaxed.gpu.global.v2.b64 {a, b}, [%4];\nmov.b64 {%0, %1}, a;\nmov.b64 {%2, %3}, b;\n}"
                        : "+r"(rr[n].x), "+r"(rr[n].y), "+r"(rr[n].z), "+r"(rr[n].w) : "l"(ap - 2048 * n), "r"(4 * n), "r"(tc - q) : "memory");
            };
            PROFK(72 + 8 * wg);
            poll();
            float2 ex[2];
            float m00[2], m01[2], m10[2], m11[2];
            {
                uint32_t z;
                asm volatile("ld.volatile.shared.u32 %0, [%1];" : "=r"(z) : "r"(sb + OFF_G + 16) : "memory");
                z = (z >> 15) & 1;
#pragma unroll
                for (int i = 0; i < 2; i++) {
                    ex[i] = make_float2(__shfl_up_sync(0xffffffffu, v[i].x, 1, 4), __shfl_up_sync(0xffffffffu, v[i].y, 1, 4));
                    if (q == 0) ex[i] = make_float2(0.f, 0.f);
                    const float cx = __uint_as_float(__float_as_uint(coef[i].x) | z), cy = __uint_as_float(__float_as_uint(coef[i].y) | z);
                    m00[i] = cx; m01[i] = -cy; m10[i] = -cy; m11[i] = -cx;
                    if (P.swapB) { m00[i] = -cy; m01[i] = cx; m10[i] = -cx; m11[i] = -cy; }
                }
            }
            auto scale = [&](int i, float& x, float& y) { const float u = fmaf(m00[i], x, m01[i] * y); y = fmaf(m10[i], x, m11[i] * y); x = u; };
#pragma unroll
            for (int i = 0; i < 2; i++) {
#pragma unroll
                for (int o = 0; o < 64; o += 4) { scale(i, acc[i][o], acc[i][o + 2]); scale(i, acc[i][o + 1], acc[i][o + 3]); }
#pragma unroll
                for (int o = 0; o < 64; o++) asm volatile("" : "+f"(acc[i][o]));
            }
            {
                PROFK(73 + 8 * wg);
#pragma unroll 1
                for (unsigned n = 0; n < SPIN_LIMIT; n++) {
                    uint32_t bad = 0;
#pragma unroll
                    for (int j = 0; j < 4; j++) bad |= (rr[j].x ^ tag) | (rr[j].z ^ tag);
                    if (!__any_sync(0xffffffffu, bad & 15)) break;
                    if (n < 3) PROFK(74 + 8 * wg + n);
                    poll();
                }
                float2 part[2] = {make_float2(__uint_as_float(rr[3].x), __uint_as_float(rr[3].y)), make_float2(__uint_as_float(rr[3].z), __uint_as_float(rr[3].w))};
#pragma unroll
                for (int n = 2; n >= 0; n--) {
                    part[0] = cfma(w4[0], part[0], make_float2(__uint_as_float(rr[n].x), __uint_as_float(rr[n].y)));
                    part[1] = cfma(w4[1], part[1], make_float2(__uint_as_float(rr[n].z), __uint_as_float(rr[n].w)));
                }
#pragma unroll
                for (int i = 0; i < 2; i++) {
                    part[i] = cmul(wq[i], part[i]);
                    part[i].x += __shfl_xor_sync(0xffffffffu, part[i].x, 1); part[i].y += __shfl_xor_sync(0xffffffffu, part[i].y, 1);
                    part[i].x += __shfl_xor_sync(0xffffffffu, part[i].x, 2); part[i].y += __shfl_xor_sync(0xffffffffu, part[i].y, 2);
                    ex[i] = cfma(l32q[i], part[i], ex[i]);
                }
            }
            if (t == 0) PROF(4 + 25 * wg);
#pragma unroll
            for (int i = 0; i < 2; i++) {
                scale(i, ex[i].x, ex[i].y);
                if (!P.swapB) { lam1[i].y = -lam1[i].y; lam8[i].y = -lam8[i].y; }
            }
            const uint32_t hs = sb + OFF_HS + ((t * 16) ^ ((t << 1) & 48));
            if (wg) mbar_wait(bars + 8 * BAR_F, 0); else bar_sync(5, 128);
#pragma unroll
            for (int i = 0; i < 2; i++) {
                if (P.ones & (4 << i)) {
#pragma unroll
                    for (int r = 0; r < 32; r++) {
                        const int o = 4 * (r >> 1) + (r & 1);
                        ex[i] = cfma(lam1[i], ex[i], make_float2(acc[i][o], acc[i][o + 2]));
                        acc[i][o] = ex[i].x; acc[i][o + 2] = ex[i].y;
                    }
                }
                if (P.ones & (16 << i)) {
#pragma unroll
                    for (int z = 0; z < 8; z++) {
                        const float* a = &acc[i][2 * z];
                        sts128u(hs + (z & 1) * 8192 + (z >> 1) * 2048 + i * 16384, pack2(a[0], a[16]), pack2(a[32], a[48]), pack2(a[1], a[17]), pack2(a[33], a[49]));
                    }
                }
                fence_proxy_async_smem();
                __syncwarp();
                if (lane == 0) mbar_arrive(bars + 8 * (BAR_HW + 2 * wg + i));
                if (i == 0) load_tw();
            }
            if (t == 0) PROF(5 + 25 * wg);
        } else load_tw();
#pragma unroll 1
        for (int ps = wg ? C0 : 0; ps < (wg ? 3 : C0); ps++) {
            if (ps != 1) {
                if (t == 0 && ps) PROF(7);
                mbar_wait(bars + (ps ? 8 * BAR_CD : 8 * BAR_U), 0);
                if (t == 0 && !ps) PROF(23);
                radix8(sb, sb + OFF_G + ps * 256, w, lane, 5);
                if (ps) break;
                bar_sync(5, 128);
                if (t == 0) PROF(22);
            }
            mbar_wait(bars + 8 * (BAR_C + ps), 0);
            phase_c(sb, 2 * w + ps, (b == 0 && ps == 0) ? (4 - w) & 3 : 3 - w, lane, tw);
            fence_proxy_async_smem();
            __syncwarp();
            if (lane == 0) mbar_arrive(bars + 8 * BAR_CD);
        }
        const int m0 = 64 * mq + 8 * w;
        auto gate_idx = [](int r) { return (r & ~126) + (r & 30) * 4 + ((r >> 4) & 6); };
        if (wg == 0) {
            if (main_cta) {
                float acc[2][64];
                int s = 33 % NS, sp = 32 % NS;
                bar_sync(3, 256);
                {
                    mbar_wait(fb + 8 * (32 % NS), (phm >> (32 % NS)) & 1);
                    phm ^= 1u << (32 % NS);
                    const uint64_t da = make_desc(sb + (32 % NS) * SLOT, 16, 1024), db = make_desc(sb + OFF_D, 128, 128, 0);
                    float sk[128];
                    wgmma_fence();
#pragma unroll
                    for (int j = 0; j < 16; j++) wgmma_n16<0>(&sk[8 * j], da + (j >> 3) * 512 + (j & 4) * 256 + (j & 3) * 2, db + 32 * (j & 7));
                    wgmma_commit();
                    wgmma_wait_all(sk);
#pragma unroll
                    for (int o = 0; o < 128; o++) acc[o >> 6][o & 63] = 0.5f * sk[o];
                }
#pragma unroll 1
                for (int k = 0; k < 28; k++) {
                    if (k == VPOS) s = (s + 4) % NS;
                    mbar_wait(fb + 8 * s, (phm >> s) & 1);
                    phm ^= 1u << s;
                    PROFK(32 + k);
                    const uint64_t da = make_desc(sb + s * SLOT, 4096, 512, 2), db = make_desc(sb + s * SLOT + 16384, 16, 1024);
                    wgmma_fence();
#pragma unroll
                    for (int j = 0; j < 4; j++) {
                        wgmma_n128<1, 0>(acc[0], da + 64 * j, db + 2 * j, 1);
                        wgmma_n128<1, 0>(acc[1], da + 512 + 64 * j, db + 2 * j, 1);
                    }
                    wgmma_commit();
                    wgmma_wait<1>();
                    if (lane == 0) mbar_arrive(bars + 8 * (BAR_EMPTY + sp));
                    __syncwarp();
                    sp = s;
                    if (++s == NS) s = 0;
                }
                float sc[2][2];
#pragma unroll
                for (int i = 0; i < 4; i++) sc[i >> 1][i & 1] = 2.f * __ldcg(&g_gate[gate_idx(8 * (m0 + 32 * (i >> 1) + 4 * (i & 1) + (g & 3)) + 2 * rp + (g >> 2))].y);
                wgmma_wait<0>();
                if (lane == 0) mbar_arrive(bars + 8 * (BAR_EMPTY + sp));
#pragma unroll
                for (int i = 0; i < 2; i++) {
#pragma unroll
                    for (int k = 0; k < 4; k++) {
                        const int s = (65 + k) % NS;
                        if (i == 0) { mbar_wait(fb + 8 * s, (phm >> s) & 1); PROFK(60 + k); }
                        const uint64_t da = make_desc(sb + s * SLOT + i * 8192, 4096, 512, 2), db = make_desc(sb + s * SLOT + 16384, 16, 1024);
                        wgmma_fence();
#pragma unroll
                        for (int j = 0; j < 4; j++) wgmma_n128<1, 0>(acc[i], da + 64 * j, db + 2 * j, 1);
                    }
                    wgmma_commit();
                }
                bar_sync(4, 256);
                const uint32_t rw = 2 * (g & 3) + (g >> 2);
                const uint32_t ob = sb + OFF_HS + w * 2048, oa = ob + rw * 128 + (((q >> 1) ^ rw) << 4) + (q & 1) * 8;
                const uint32_t ea = sb + OFF_U + (16 * w + (lane & 15)) * 128 + (((lane >> 4) ^ (lane & 7) ^ ((lane >> 1) & 4)) << 4);
#pragma unroll
                for (int i = 0; i < 2; i++) {
                    uint32_t e[8][4];
#pragma unroll
                    for (int j = 0; j < 8; j++) ldsm_x4(e[j], (ea ^ ((j & 3) << 5)) + (j >> 2) * 16384 + i * 8192);
                    if (i) wgmma_wait<0>(); else wgmma_wait<1>();
#pragma unroll
                    for (int o = 0; o < 64; o++) asm volatile("" : "+f"(acc[i][o]) :: "memory");
                    if (tid == 0) PROF(17 + i);
                    if (tid == 96 && i) PROFG(20);
#pragma unroll
                    for (int c = 0; c < 4; c++) {
#pragma unroll
                        for (int j = 0; j < 8; j++) {
                            const int o = 16 * c + 2 * j;
                            const uint32_t ev = e[2 * c + (j >> 2)][j & 3];
                            sts64((oa ^ ((j >> 1) << 5)) + c * 8192 + i * 65536 + (j & 1) * 1024,
                                  fmaf(sc[i][j & 1], acc[i][o], bf_lo(ev)), fmaf(sc[i][j & 1], acc[i][o + 1], bf_hi(ev)));
                        }
                        fence_proxy_async_smem();
                        __syncwarp();
                        if (elect()) tma_store_4d(&mapO, ob + c * 8192 + i * 65536, 128 * dt + 32 * c, 0, rp, m0 + 32 * i);
                    }
                }
                if (elect()) {
                    bulk_commit();
                    asm volatile("cp.async.bulk.wait_group.read 0;" ::: "memory");
                }
                if (tid == 0) PROF(19);
                if (tid == 96) { PROF(20); PROFG(4); }
            }
        } else {
            fence_proxy_async_smem();
            __syncwarp();
            if (lane == 0) mbar_arrive(bars + 8 * BAR_VW);
            if (t == 0) PROF(24);
            if (tid == 224) PROFG(16);
            if (main_cta) {
                float acc[2][64];
                mbar_wait(bars + 8 * BAR_T, 0);
#pragma unroll
                for (int k = 0; k < 4; k++) {
                    const int s = (33 + VPOS + k) % NS;
                    mbar_wait(fb + 8 * s, (phm >> s) & 1);
                    PROFK(64 + k);
                    const uint64_t da = make_desc(sb + OFF_HS + k * 8192, 4096, 512, 2), db = make_desc(sb + s * SLOT, 8192, 1024);
                    wgmma_fence();
#pragma unroll
                    for (int j = 0; j < 4; j++) {
                        wgmma_n128<1, 1>(acc[0], da + 64 * j, db + 128 * j, (k | j) != 0);
                        wgmma_n128<1, 1>(acc[1], da + 64 * j, db + 1024 + 128 * j, (k | j) != 0);
                    }
                    wgmma_commit();
                    if (k) {
                        wgmma_wait<1>();
                        if (lane == 0) mbar_arrive(bars + 8 * (BAR_EMPTY + (32 + VPOS + k) % NS));
                        __syncwarp();
                    }
                }
                float4 gt[2];
#pragma unroll
                for (int i = 0; i < 2; i++) gt[i] = __ldcg((const float4*)&g_gate[gate_idx(8 * (m0 + 8 * w + 8 * i + g) + 2 * rp)]);
                const uint32_t ea = sb + OFF_U + (32 * w + 2 * (lane & 12) + (lane & 3)) * 128 + (((lane >> 4) ^ (lane & 7)) << 4);
                wgmma_wait_all(acc[0]);
#pragma unroll
                for (int o = 0; o < 64; o++) asm volatile("" : "+f"(acc[1][o]) :: "memory");
                if (lane == 0) mbar_arrive(bars + 8 * (BAR_EMPTY + (36 + VPOS) % NS));
                if (t == 0) PROF(15);
#pragma unroll
                for (int e = 0; e < 2; e++) {
                    const uint32_t g0 = __byte_perm(__float_as_uint(e ? gt[0].z : gt[0].x), 0, 0x3232), g1 = __byte_perm(__float_as_uint(e ? gt[1].z : gt[1].x), 0, 0x3232);
#pragma unroll
                    for (int j = 0; j < 8; j++) {
                        const float* a = &acc[e][8 * j];
                        stsm_x4((ea ^ ((j & 3) << 5) ^ (e << 6)) + e * 512 + (j >> 2) * 16384, bf_mul2(pack2(a[0], a[1]), g0), bf_mul2(pack2(a[2], a[3]), g1),
                                bf_mul2(pack2(a[4], a[5]), g0), bf_mul2(pack2(a[6], a[7]), g1));
                    }
                }
                bar_arrive(4, 256);
                if (t == 0) PROF(16);
            }
            if (t == 0) {
                const unsigned old = atomicAdd(&g_cnt[CNT_DONE * 32], 1u);
                if (old == 128) { g_cnt[CNT_DONE * 32] = 0; g_cnt[CNT_EPOCH * 32] = epoch; }
            }
        }
    } else {
        reg_dealloc<72>();
        if (elect()) {
            if (warp == 10) asm volatile("prefetch.tensormap [%0];" :: "l"(&mapH) : "memory");
            if (warp == 8) {
                PROF(0);
#pragma unroll
                for (int i = 0; i < 5; i++) mbar_init(bars + 8 * i, 1);
                mbar_init(bars + 8 * BAR_X, 1);
                fence_barrier_init();
                fence_proxy_async_smem();
                if (main_cta) {
#pragma unroll 1
                    for (int k = 0; k < NS; k++) {
                        load_g1(k, k);
                        if (k == 0) bulk_load(sb + OFF_GW, P.gate_w, 2048, bars);
                        load_xs(k);
                    }
                }
                PROF(27);
            }
            if (warp == 9) {
#pragma unroll
                for (int i = 5; i < NBAR; i++) if (i != BAR_X) mbar_init(bars + 8 * i, i < BAR_EMPTY ? 1 : i < BAR_CD ? 4 : i < BAR_C ? 8 : 64);
                fence_barrier_init();
                fence_proxy_async_smem();
            }
        }
        __syncwarp();
        bar_sync(0, 384);
        const int w = warp - 8;
        if (w == 0) {
            if (main_cta && elect()) {
                int s = 0; uint32_t ph = 0;
#pragma unroll 1
                for (int k = NS; k < 69; k++) {
                    mbar_wait(bars + 8 * (BAR_EMPTY + s), ph);
                    if (k < 32) {
                        load_g1(k, s);
                        load_xs(k);
                    }
                    else {
                        const uint32_t st = sb + s * SLOT;
                        const unsigned kv = k - 33 - VPOS;
                        if (kv < 4) {
                            const uint32_t full = bars + 8 * (BAR_FULL + 5 + s);
                            if (kv == 0) mbar_wait(bars + 8 * (BAR_F + 2), 0);
                            mbar_expect_tx(full, SLOT);
                            tma_load_3d(st, &mapV, full, 0, kv * 64, rp * 32 + dt * 2);
                            tma_load_3d(st + 16384, &mapV, full, 0, kv * 64, rp * 32 + 16 + dt * 2);
                        } else if (k == 32) {
                            const uint32_t full = bars + 8 * (BAR_FULL + s);
                            mbar_expect_tx(full, SLOT);
                            tma_load_4d(st, &mapXe, full, 128 * dt, 0, 2 * rp, 16 * mq);
                            tma_load_4d(st + 16384, &mapXe, full, 128 * dt + 64, 0, 2 * rp, 16 * mq);
                        } else {
                            const uint32_t full = bars + 8 * (BAR_FULL + s);
                            const int h = k < 33 + VPOS ? k - 33 : k - 37;
                            mbar_expect_tx(full, SLOT);
                            tma_load_3d(st + 16384, &mapCre + (h & 1), full, 0, dt * 128, h >> 1);
                            if ((h & 15) == 0) mbar_wait(bars + 8 * (BAR_F + (h >> 4)), 0);
                            bulk_load(st, g_hT + (h * 16 + tc) * 16384, 16384, full);
                        }
                    }
                    if (++s == NS) { s = 0; ph ^= 1; }
                }
            }
        } else if (w == 1) {
            if (elect()) {
                const unsigned epoch = load_epoch();
                mbar_wait(bars + 8 * BAR_S1, 0);
                if (main_cta) {
#pragma unroll
                    for (int c = 0; c < 4; c++) {
                        if (c) pause(PACE_U);
                        tma_store_4d(&mapU0, sb + OFF_U + c * 8192, (b & 15) * 64, 32 * c, 0, b >> 4);
                    }
                    bulk_commit();
                    bulk_wait0();
                    signal_counter(&g_cnt[CNT_U * 32]);
                }
                PROF(9);
                mbar_expect_tx(bars + 8 * BAR_U, 32768);
                wait_counter(&g_cnt[CNT_U * 32], epoch * 128);
                PROF(11);
#pragma unroll
                for (int i = 0; i < 8; i++) {
                    if (i && !(i & 1)) pause(PACE_L);
                    tma_load_4d(sb + OFF_U + i * 4096, &mapU2, bars + 8 * BAR_U, 0, 0, (i & 3) * 4, b == 128 ? 1 : b == 0 ? 0 : 2 * b + (i >> 2));
                }
                if (main_cta) {
#pragma unroll 1
                    for (int i = 0; i < 2; i++) {
#pragma unroll
                        for (int j = 0; j < 8; j++) {
                            if (j & 3) pause(PACE_H);
                            else mbar_wait(bars + 8 * (BAR_HW + 2 * i + (j >> 2)), 0);
                            tma_store_3d(&mapH, sb + OFF_HS + j * 4096, 0, 2 * tc + (j >> 2), (dt + 8 * i) * 8 + (j & 3) * 2);
                            if (j == 0) bulk_store(g_gate + tc * 128 + dt * 16 + i * 8, sb + OFF_GS + 64 * i, 64);
                        }
                        bulk_commit();
                        bulk_wait0();
                        signal_counter(&g_cnt[(CNT_H + i) * 32]);
                        PROF(i ? 6 : 26);
                        if (i) {
                            mbar_expect_tx(bars + 8 * BAR_T, 32768);
#pragma unroll
                            for (int j = 0; j < 4; j++) bulk_load(sb + OFF_HS + j * 8192, c_inv + mq * 4096 + j * 1024, 8192, bars + 8 * BAR_T);
                        }
                        wait_counter(&g_cnt[(CNT_H + i) * 32], epoch * 128);
                        mbar_arrive(bars + 8 * (BAR_F + i));
                        PROF(1 + i);
                    }
                }
                mbar_wait(bars + 8 * BAR_VW, 0);
#pragma unroll
                for (int i = 0; i < 8; i++) {
                    if (i == 4 && real_cls) break;
                    if (i) pause(PACE_V);
                    tma_store_4d(&mapU2, sb + OFF_U + i * 4096, 0, 0, (i & 3) * 4, b == 128 ? 1 : 2 * b + (i >> 2));
                }
                bulk_commit();
                bulk_wait0();
                signal_counter(&g_cnt[CNT_V * 32]);
                PROF(13);
                if (main_cta) {
                    wait_counter(&g_cnt[CNT_V * 32], epoch * 129);
                    mbar_arrive(bars + 8 * (BAR_F + 2));
                    PROF(14);
                }
            }
        } else {
            const int ld = (1026 * cls) >> 7, lm = (1026 * ((256 - cls) & 255)) >> 7;
#pragma unroll 1
            for (int ps = 0; ps < 2; ps++) {
                if (elect()) {
                    if (w == 2) {
                        const uint32_t bw = bars + 8 * BAR_W;
                        if (ps) mbar_wait(bars + 8 * BAR_WR, 0);
                        else {
                            pause(PF_BA);
                            if (main_cta) bulk_prefetch_l2(((b & 1) ? P.b_im : P.b_re) + (b >> 1) * 8192, 16384);
                            pause(T_B2);
                            if (main_cta) bulk_prefetch_l2(((b & 1) ? P.b_im : P.b_re) + (64 + (b >> 1)) * 8192, 16384);
                            pause(T_W0);
                        }
                        mbar_expect_tx(bw, ps ? 18432 : 18432 + 8192);
#pragma unroll
                        for (int i = 0; i < 4; i++)
                            tma_load_4d(sb + OFF_W + (i >> 1) * 4608 + (i & 1) * 9216, &mapWr + (i & 1), bw, 0, i < 2 ? ld : lm, (i < 2 || b == 0) ? ps : 1 - ps, 0);
                        if (!ps) bulk_load(sb + OFF_F, c_tab + 8192, 8192, bw);
                    } else if (!ps) {
                        pause(T_W);
#pragma unroll
                        for (int i = 0; i < 4; i++) {
                            tma_prefetch_4d(&mapWr + (i & 1), 0, i < 2 ? ld : lm, (i < 2 || b == 0) ? 1 : 0, 0);
                            pause(200);
                        }
                        if (main_cta) bulk_prefetch_l2(c_inv + b * 128, 1024);
                    }
                }
                __syncwarp();
                mbar_wait(bars + 8 * BAR_W, ps);
                if (tid == 320) PROF(ps ? 31 : 10);
#pragma unroll 1
                for (int u = 0; u < 4; u++) {
                    const int row = 2 * (w - 2) + (u >> 1), pl = u & 1;
                    const uint32_t dp = sb + OFF_W + pl * 9216 + row * 1152, mp = sb + OFF_W + pl * 9216 + 4608 + ((b == 0 && ps == 0) ? (4 - row) & 3 : 3 - row) * 1152;
                    const uint32_t od = dp + ((1026 * cls) & 127), om = mp + ((1026 * (256 - cls)) & 127);
                    uint32_t v[16][2];
#pragma unroll
                    for (int i = 0; i < 8; i++) {
                        const uint32_t a = od + 4 * lane + 128 * i, c = om - 4 * lane + 1024 - 128 * i;
                        v[i][0] = lds16(a); v[i][1] = lds16(a + 2);
                        v[8 + i][0] = lds16(c); v[8 + i][1] = lds16(c - 2);
                    }
                    const uint32_t e0 = lds16(om), e1 = lds16(od + 1024);
                    __syncwarp();
                    if (lane == 0) {
                        v[0][0] = pack2(fmaf(pl ? -0.5f : 0.5f, bf_lo(e0), 0.5f * bf_lo(v[0][0])), 0.f);
                        v[8][0] = pack2(fmaf(pl ? -0.5f : 0.5f, bf_lo(e1), 0.5f * bf_lo(v[8][0])), 0.f);
                    }
                    const uint32_t sg = pl ? 0x80008000u : 0u;
#pragma unroll
                    for (int i = 0; i < 16; i++)
                        sts32((i < 8 ? dp : mp) + (i & 7) * 128 + ((lane * 4) ^ ((i & 3) << 4)), __byte_perm(v[i][0], v[i][1], 0x5410) ^ (i >= 8 ? sg : 0u));
                }
                mbar_arrive(bars + 8 * (BAR_C + ps));
                if (tid == 320 && ps) PROF(12);
                if (w == 3 && !ps && main_cta && elect()) {
#pragma unroll 1
                    for (int i = 0; i < 8; i++) {
                        bulk_prefetch_l2(((b & 1) ? P.c_im : P.c_re) + (size_t)(b >> 1) * 16384 + i * 2048, 4096);
                        pause(300);
                    }
                }
                __syncwarp();
            }
        }
    }
}

typedef CUresult (*PFN_encodeTiled)(CUtensorMap*, CUtensorMapDataType, cuuint32_t, void*, const cuuint64_t*, const cuuint64_t*,
                                    const cuuint32_t*, const cuuint32_t*, CUtensorMapInterleave, CUtensorMapSwizzle,
                                    CUtensorMapL2promotion, CUtensorMapFloatOOBfill);

static CUtensorMap make_map(PFN_encodeTiled enc, const void* ptr, int rank, const cuuint64_t* dims, const cuuint64_t* strides, const cuuint32_t* box,
                            CUtensorMapSwizzle sw = CU_TENSOR_MAP_SWIZZLE_128B, CUtensorMapDataType dt = CU_TENSOR_MAP_DATA_TYPE_BFLOAT16) {
    CUtensorMap m;
    cuuint32_t es[5] = {1, 1, 1, 1, 1};
    enc(&m, dt, rank, (void*)ptr, dims, strides, box, es, CU_TENSOR_MAP_INTERLEAVE_NONE,
        sw, CU_TENSOR_MAP_L2_PROMOTION_L2_128B, CU_TENSOR_MAP_FLOAT_OOB_FILL_NONE);
    return m;
}

extern "C" void kernel_launch(void* const* d_in, const int* in_sizes, int n_in, void* d_out, int out_size) {
    const bf16* x = (const bf16*)d_in[0];
    const bf16* wr = (const bf16*)d_in[1];
    const bf16* wi = (const bf16*)d_in[2];
    const bf16* Bre = (const bf16*)d_in[6];
    const bf16* Bim = (const bf16*)d_in[7];
    const bf16* Cre = (const bf16*)d_in[8];
    const bf16* Cim = (const bf16*)d_in[9];

    void* fn = nullptr;
    cudaDriverEntryPointQueryResult st;
    cudaGetDriverEntryPoint("cuTensorMapEncodeTiled", &fn, cudaEnableDefault, &st);
    PFN_encodeTiled enc = (PFN_encodeTiled)fn;
    void *p_hT, *p_U;
    cudaGetSymbolAddress(&p_hT, g_hT);
    cudaGetSymbolAddress(&p_U, g_U);

    Params P;
    P.lam_re = (const bf16*)d_in[4]; P.lam_im = (const bf16*)d_in[5]; P.log_dt = (const bf16*)d_in[10];
    P.dskip = (const bf16*)d_in[11]; P.gate_w = (const bf16*)d_in[12]; P.c_re = Cre; P.c_im = Cim; P.b_re = Bre; P.b_im = Bim;
    P.swapB = Bim < Bre;
    P.ones = -1;

    for (int c = 0; c < 68; c++) P.perm[c] = c < 4 ? 32 + 8 * c : c < 36 ? ((c - 4) & 24) + ((c - 5) & 7) : c < 64 ? 32 + (c - 36) / 7 * 8 + ((c - 37 + 7) % 7 + 1) : c;

    CUtensorMap mB, mX, mCre, mCim, mXs, mU0, mV, mU2, mXe, mO, mWr, mWi, mH;
    {
        cuuint64_t d[4] = {64, 2052, 2, 4}, s[3] = {128, 262656, 525312};
        cuuint32_t bx[4] = {64, 9, 1, 4};
        mWr = make_map(enc, wr, 4, d, s, bx, CU_TENSOR_MAP_SWIZZLE_NONE);
        mWi = make_map(enc, wi, 4, d, s, bx, CU_TENSOR_MAP_SWIZZLE_NONE);
    }
    {
        cuuint64_t d[3] = {256, 32, 128}, s[2] = {2048, 65536};
        cuuint32_t bx[3] = {256, 1, 2};
        mH = make_map(enc, p_hT, 3, d, s, bx, CU_TENSOR_MAP_SWIZZLE_NONE, CU_TENSOR_MAP_DATA_TYPE_UINT64);
    }
    {
        const bf16* lo = P.swapB ? Bim : Bre; const bf16* hi = P.swapB ? Bre : Bim;
        cuuint64_t d[4] = {1024, 8, 2, 128}, s[3] = {2048, (cuuint64_t)((const char*)hi - (const char*)lo), 16384};
        cuuint32_t bx[4] = {64, 8, 2, 8};
        mB = make_map(enc, lo, 4, d, s, bx);
    }
    {
        cuuint64_t d[4] = {1024, 2, 4, 976}, s[3] = {2048, 32 * 2048, 2 * 2048};
        cuuint32_t bx[4] = {64, 2, 4, 16};
        mX = make_map(enc, x, 4, d, s, bx);
    }
    {
        cuuint64_t d[3] = {64, 1024, 16}, s[2] = {2048, 128};
        cuuint32_t bx[3] = {64, 128, 1};
        mCre = make_map(enc, Cre, 3, d, s, bx);
        mCim = make_map(enc, Cim, 3, d, s, bx);
    }
    {
        cuuint64_t d[3] = {64, 256, 128}, s[2] = {16384, 128};
        cuuint32_t bx[3] = {64, 64, 2};
        mV = make_map(enc, p_U, 3, d, s, bx);
    }
    {
        cuuint64_t d[4] = {1024, 4, 8, 64}, s[3] = {8 * 2048, 2048, 32 * 2048};
        cuuint32_t bx[4] = {64, 4, 2, 16};
        mXe = make_map(enc, x, 4, d, s, bx);
    }
    {
        cuuint64_t d[4] = {1024, 2, 4, 256}, s[3] = {4096, 2 * 4096, 8 * 4096};
        cuuint32_t bx[4] = {32, 2, 1, 8};
        mO = make_map(enc, d_out, 4, d, s, bx, CU_TENSOR_MAP_SWIZZLE_128B, CU_TENSOR_MAP_DATA_TYPE_FLOAT32);
    }
    {
        cuuint64_t d[4] = {1024, 64, 4, 8}, s[3] = {32 * 2048, 8 * 2048, 2048};
        cuuint32_t bx[4] = {64, 64, 1, 1};
        mXs = make_map(enc, x, 4, d, s, bx);
    }
    {
        cuuint64_t d[4] = {1024, 128, 2, 8}, s[3] = {32768, 16384, 2048};
        cuuint32_t bx[4] = {64, 32, 2, 1};
        mU0 = make_map(enc, p_U, 4, d, s, bx);
    }
    {
        cuuint64_t d[4] = {64, 8, 16, 256}, s[3] = {2048, 128, 16384};
        cuuint32_t bx[4] = {64, 8, 4, 1};
        mU2 = make_map(enc, p_U, 4, d, s, bx);
    }
    cudaFuncSetAttribute(fused_kernel, cudaFuncAttributeMaxDynamicSharedMemorySize, SMEM_BYTES);
    fused_kernel<<<130, 384, SMEM_BYTES, cudaStreamPerThread>>>(mB, mX, mXs, mU0, mU2, mXe, mCre, mCim, mV, mO, mWr, mWi, mH, P);
}
```

```cpp
#include <cuda_runtime.h>
#include <cuda_bf16.h>
#include <cuda.h>
#include <stdint.h>

typedef __nv_bfloat16 bf16;

__device__ const __align__(128) uint32_t c_tab[11264] = {
0x3f803f80,0xbf803f80,0x3f803f80,0xbf803f80,0x3f803f80,0xbf803f80,0x3f803f80,0xbf803f80,0x3f803f80,0xbf803f80,0x3f803f80,0xbf803f80,
0x3f803f80,0xbf803f80,0x3f803f80,0xbf803f80,0x3f7f3f80,0xbdc98000,0x3f223f35,0xbf46bf35,0x3f753f7b,0xbe95be48,0x3ef13f0e,0xbf62bf55,
0x3f623f6d,0xbef1bec4,0x3e953ec4,0xbf75bf6d,0x3f463f55,0xbf22bf0e,0x3dc93e48,0xbf7fbf7b,0x3f7b3f80,0xbe488000,0xbe480000,0xbf7bbf80,
0x3f553f6d,0xbf0ebec4,0xbf0ebec4,0xbf55bf6d,0x3f0e3f35,0xbf55bf35,0xbf55bf35,0xbf0ebf35,0x3e483ec4,0xbf7bbf6d,0xbf7bbf6d,0xbe48bec4,
0x3f753f80,0xbe958000,0xbf62bf35,0xbef1bf35,0x3f223f55,0xbf46bf0e,0xbf7fbf7b,0x3dc9be48,0x3dc93ec4,0xbf7fbf6d,0xbf46bf6d,0x3f223ec4,
0xbef1be48,0xbf62bf7b,0xbe95bf0e,0x3f753f55,0x3f6d3f80,0xbec48000,0xbf6dbf80,0x3ec48000,0x3ec43f35,0xbf6dbf35,0xbec4bf35,0x3f6d3f35,
0xbec40000,0xbf6dbf80,0x3ec40000,0x3f6d3f80,0xbf6dbf35,0xbec4bf35,0x3f6d3f35,0x3ec43f35,0x3f623f80,0xbef18000,0xbe95bf35,0x3f753f35,
0x3dc93f0e,0xbf7fbf55,0x3f223e48,0x3f463f7b,0xbf46bec4,0xbf22bf6d,0x3f7f3f6d,0xbdc93ec4,0xbf75bf7b,0x3e95be48,0x3ef13f55,0xbf62bf0e,
0x3f553f80,0xbf0e8000,0x3f0e0000,0x3f553f80,0xbe483ec4,0xbf7bbf6d,0x3f7b3f6d,0xbe483ec4,0xbf7bbf35,0xbe48bf35,0x3e483f35,0xbf7bbf35,
0xbf0ebf6d,0x3f553ec4,0xbf55bec4,0xbf0ebf6d,0x3f463f80,0xbf228000,0x3f7f3f35,0x3dc93f35,0xbef13e48,0xbf62bf7b,0x3e953f55,0xbf75bf0e,
0xbf75bf6d,0x3e95bec4,0xbf62bec4,0xbef1bf6d,0x3dc9bf0e,0x3f7f3f55,0xbf22bf7b,0x3f463e48,0x3f353f80,0xbf358000,0x3f353f80,0xbf358000,
0xbf350000,0xbf35bf80,0xbf350000,0xbf35bf80,0xbf35bf80,0x3f358000,0xbf35bf80,0x3f358000,0x3f350000,0x3f353f80,0x3f350000,0x3f353f80,
0x3f223f80,0xbf468000,0xbdc93f35,0xbf7fbf35,0xbf62be48,0xbef1bf7b,0xbf75bf55,0x3e95bf0e,0xbe95bf6d,0x3f753ec4,0x3ef1bec4,0x3f623f6d,
0x3f7f3f0e,0x3dc93f55,0x3f463f7b,0xbf223e48,0x3f0e3f80,0xbf558000,0xbf550000,0xbf0ebf80,0xbf7bbec4,0xbe48bf6d,0xbe48bf6d,0x3f7b3ec4,
0x3e48bf35,0x3f7b3f35,0x3f7b3f35,0xbe483f35,0x3f553f6d,0xbf0e3ec4,0xbf0e3ec4,0xbf55bf6d,0x3ef13f80,0xbf628000,0xbf75bf35,0x3e95bf35,
0xbf7fbf0e,0x3dc9bf55,0x3f46be48,0x3f223f7b,0x3f22bec4,0x3f463f6d,0x3dc93f6d,0xbf7fbec4,0x3e953f7b,0xbf75be48,0xbf62bf55,0x3ef1bf0e,
0x3ec43f80,0xbf6d8000,0xbec4bf80,0x3f6d8000,0xbf6dbf35,0x3ec4bf35,0x3f6d3f35,0xbec43f35,0x3f6d0000,0x3ec43f80,0xbf6d0000,0xbec4bf80,
0xbec43f35,0xbf6dbf35,0x3ec4bf35,0x3f6d3f35,0x3e953f80,0xbf758000,0x3ef1bf35,0x3f623f35,0xbf46bf55,0x3f22bf0e,0x3dc93f7b,0xbf7fbe48,
0x3f7f3ec4,0xbdc93f6d,0xbf22bf6d,0x3f46bec4,0xbf623e48,0xbef1bf7b,0x3f753f0e,0xbe953f55,0x3e483f80,0xbf7b8000,0x3f7b0000,0x3e483f80,
0xbf0ebf6d,0x3f55bec4,0xbf553ec4,0xbf0ebf6d,0x3f553f35,0xbf0e3f35,0x3f0ebf35,0x3f553f35,0xbf7bbec4,0x3e48bf6d,0xbe483f6d,0xbf7bbec4,
0x3dc93f80,0xbf7f8000,0x3f463f35,0xbf223f35,0xbe95bf7b,0x3f75be48,0xbf62bf0e,0x3ef1bf55,0x3ef13f6d,0xbf623ec4,0x3f753ec4,0xbe953f6d,
0xbf22bf55,0x3f46bf0e,0xbf7fbe48,0x3dc9bf7b,0x3f80,0xbf808000,0x3f80,0xbf808000,0xbf80,0x3f808000,0xbf80,0x3f808000,
0x3f80,0xbf808000,0x3f80,0xbf808000,0xbf80,0x3f808000,0xbf80,0x3f808000,0xbdc93f80,0xbf7f8000,0xbf463f35,0xbf22bf35,
0x3e95bf7b,0x3f753e48,0x3f62bf0e,0x3ef13f55,0xbef13f6d,0xbf62bec4,0xbf753ec4,0xbe95bf6d,0x3f22bf55,0x3f463f0e,0x3f7fbe48,0x3dc93f7b,
0xbe483f80,0xbf7b8000,0xbf7b0000,0x3e48bf80,0x3f0ebf6d,0x3f553ec4,0x3f553ec4,0xbf0e3f6d,0xbf553f35,0xbf0ebf35,0xbf0ebf35,0x3f55bf35,
0x3f7bbec4,0x3e483f6d,0x3e483f6d,0xbf7b3ec4,0xbe953f80,0xbf758000,0xbef1bf35,0x3f62bf35,0x3f46bf55,0x3f223f0e,0xbdc93f7b,0xbf7f3e48,
0xbf7f3ec4,0xbdc9bf6d,0x3f22bf6d,0x3f463ec4,0x3f623e48,0xbef13f7b,0xbf753f0e,0xbe95bf55,0xbec43f80,0xbf6d8000,0x3ec4bf80,0x3f6d8000,
0x3f6dbf35,0x3ec43f35,0xbf6d3f35,0xbec4bf35,0xbf6d0000,0x3ec4bf80,0x3f6d0000,0xbec43f80,0x3ec43f35,0xbf6d3f35,0xbec4bf35,0x3f6dbf35,
0xbef13f80,0xbf628000,0x3f75bf35,0x3e953f35,0x3f7fbf0e,0x3dc93f55,0xbf46be48,0x3f22bf7b,0xbf22bec4,0x3f46bf6d,0xbdc93f6d,0xbf7f3ec4,
0xbe953f7b,0xbf753e48,0x3f62bf55,0x3ef13f0e,0xbf0e3f80,0xbf558000,0x3f550000,0xbf0e3f80,0x3f7bbec4,0xbe483f6d,0x3e48bf6d,0x3f7bbec4,
0xbe48bf35,0x3f7bbf35,0xbf7b3f35,0xbe48bf35,0xbf553f6d,0xbf0ebec4,0x3f0e3ec4,0xbf553f6d,0xbf223f80,0xbf468000,0x3dc93f35,0xbf7f3f35,
0x3f62be48,0xbef13f7b,0x3f75bf55,0x3e953f0e,0x3e95bf6d,0x3f75bec4,0xbef1bec4,0x3f62bf6d,0xbf7f3f0e,0x3dc9bf55,0xbf463f7b,0xbf22be48,
0xbf353f80,0xbf358000,0xbf353f80,0xbf358000,0x3f350000,0xbf353f80,0x3f350000,0xbf353f80,0x3f35bf80,0x3f358000,0x3f35bf80,0x3f358000,
0xbf350000,0x3f35bf80,0xbf350000,0x3f35bf80,0xbf463f80,0xbf228000,0xbf7f3f35,0x3dc9bf35,0x3ef13e48,0xbf623f7b,0xbe953f55,0xbf753f0e,
0x3f75bf6d,0x3e953ec4,0x3f62bec4,0xbef13f6d,0xbdc9bf0e,0x3f7fbf55,0x3f22bf7b,0x3f46be48,0xbf553f80,0xbf0e8000,0xbf0e0000,0x3f55bf80,
0x3e483ec4,0xbf7b3f6d,0xbf7b3f6d,0xbe48bec4,0x3f7bbf35,0xbe483f35,0xbe483f35,0xbf7b3f35,0x3f0ebf6d,0x3f55bec4,0x3f55bec4,0xbf0e3f6d,
0xbf623f80,0xbef18000,0x3e95bf35,0x3f75bf35,0xbdc93f0e,0xbf7f3f55,0xbf223e48,0x3f46bf7b,0x3f46bec4,0xbf223f6d,0xbf7f3f6d,0xbdc9bec4,
0x3f75bf7b,0x3e953e48,0xbef13f55,0xbf623f0e,0xbf6d3f80,0xbec48000,0x3f6dbf80,0x3ec48000,0xbec43f35,0xbf6d3f35,0x3ec4bf35,0x3f6dbf35,
0x3ec40000,0xbf6d3f80,0xbec40000,0x3f6dbf80,0x3f6dbf35,0xbec43f35,0xbf6d3f35,0x3ec4bf35,0xbf753f80,0xbe958000,0x3f62bf35,0xbef13f35,
0xbf223f55,0xbf463f0e,0x3f7fbf7b,0x3dc93e48,0xbdc93ec4,0xbf7f3f6d,0x3f46bf6d,0x3f22bec4,0x3ef1be48,0xbf623f7b,0x3e95bf0e,0x3f75bf55,
0xbf7b3f80,0xbe488000,0x3e480000,0xbf7b3f80,0xbf553f6d,0xbf0e3ec4,0x3f0ebec4,0xbf553f6d,0xbf0e3f35,0xbf553f35,0x3f55bf35,0xbf0e3f35,
0xbe483ec4,0xbf7b3f6d,0x3f7bbf6d,0xbe483ec4,0xbf7f3f80,0xbdc98000,0xbf223f35,0xbf463f35,0xbf753f7b,0xbe953e48,0xbef13f0e,0xbf623f55,
0xbf623f6d,0xbef13ec4,0xbe953ec4,0xbf753f6d,0xbf463f55,0xbf223f0e,0xbdc93e48,0xbf7f3f7b,0x3f803f80,0xbf803f80,0x3f803f80,0xbf803f80,
0x3f803f80,0xbf803f80,0x3f803f80,0xbf803f80,0x3f803f80,0xbf803f80,0x3f803f80,0xbf803f80,0x3f803f80,0xbf803f80,0x3f803f80,0xbf803f80,
0xbdc90000,0xbf7fbf80,0xbf46bf35,0xbf22bf35,0xbe95be48,0xbf75bf7b,0xbf62bf55,0xbef1bf0e,0xbef1bec4,0xbf62bf6d,0xbf75bf6d,0xbe95bec4,
0xbf22bf0e,0xbf46bf55,0xbf7fbf7b,0xbdc9be48,0xbf7bbf80,0x3e488000,0x3e480000,0x3f7b3f80,0xbf55bf6d,0x3f0e3ec4,0x3f0e3ec4,0x3f553f6d,
0xbf0ebf35,0x3f553f35,0x3f553f35,0x3f0e3f35,0xbe48bec4,0x3f7b3f6d,0x3f7b3f6d,0x3e483ec4,0x3e950000,0x3f753f80,0x3ef13f35,0xbf62bf35,
0x3f463f0e,0x3f223f55,0xbdc93e48,0xbf7fbf7b,0x3f7f3f6d,0x3dc93ec4,0xbf22bec4,0xbf46bf6d,0x3f623f7b,0xbef1be48,0xbf75bf55,0xbe95bf0e,
0x3f6d3f80,0xbec48000,0xbf6dbf80,0x3ec48000,0x3ec43f35,0xbf6dbf35,0xbec4bf35,0x3f6d3f35,0xbec40000,0xbf6dbf80,0x3ec40000,0x3f6d3f80,
0xbf6dbf35,0xbec4bf35,0x3f6d3f35,0x3ec43f35,0xbef10000,0xbf62bf80,0x3f753f35,0x3e953f35,0xbf7fbf55,0xbdc9bf0e,0x3f463f7b,0xbf22be48,
0xbf22bf6d,0x3f463ec4,0xbdc93ec4,0xbf7fbf6d,0x3e95be48,0x3f753f7b,0xbf62bf0e,0xbef1bf55,0xbf55bf80,0x3f0e8000,0xbf0e0000,0xbf55bf80,
0x3e48bec4,0x3f7b3f6d,0xbf7bbf6d,0x3e48bec4,0x3f7b3f35,0x3e483f35,0xbe48bf35,0x3f7b3f35,0x3f0e3f6d,0xbf55bec4,0x3f553ec4,0x3f0e3f6d,
0x3f220000,0x3f463f80,0xbdc9bf35,0x3f7f3f35,0x3f623f7b,0xbef13e48,0x3f753f0e,0x3e953f55,0xbe953ec4,0xbf75bf6d,0x3ef13f6d,0xbf62bec4,
0xbf7fbf55,0x3dc9bf0e,0xbf46be48,0xbf22bf7b,0x3f353f80,0xbf358000,0x3f353f80,0xbf358000,0xbf350000,0xbf35bf80,0xbf350000,0xbf35bf80,
0xbf35bf80,0x3f358000,0xbf35bf80,0x3f358000,0x3f350000,0x3f353f80,0x3f350000,0x3f353f80,0xbf460000,0xbf22bf80,0xbf7fbf35,0x3dc9bf35,
0xbef1bf7b,0x3f623e48,0x3e95bf0e,0x3f753f55,0x3f753ec4,0x3e953f6d,0x3f623f6d,0xbef13ec4,0x3dc93f55,0xbf7fbf0e,0xbf223e48,0xbf46bf7b,
0xbf0ebf80,0x3f558000,0x3f550000,0x3f0e3f80,0x3f7b3ec4,0x3e483f6d,0x3e483f6d,0xbf7bbec4,0xbe483f35,0xbf7bbf35,0xbf7bbf35,0x3e48bf35,
0xbf55bf6d,0x3f0ebec4,0x3f0ebec4,0x3f553f6d,0x3f620000,0x3ef13f80,0xbe953f35,0xbf75bf35,0xbdc93f55,0xbf7fbf0e,0xbf22bf7b,0x3f46be48,
0xbf46bf6d,0x3f22bec4,0x3f7f3ec4,0x3dc93f6d,0x3f753e48,0x3e953f7b,0xbef13f0e,0xbf62bf55,0x3ec43f80,0xbf6d8000,0xbec4bf80,0x3f6d8000,
0xbf6dbf35,0x3ec4bf35,0x3f6d3f35,0xbec43f35,0x3f6d0000,0x3ec43f80,0xbf6d0000,0xbec4bf80,0xbec43f35,0xbf6dbf35,0x3ec4bf35,0x3f6d3f35,
0xbf750000,0xbe95bf80,0x3f623f35,0xbef13f35,0x3f22bf0e,0x3f463f55,0xbf7fbe48,0xbdc9bf7b,0xbdc93f6d,0xbf7fbec4,0x3f46bec4,0x3f223f6d,
0xbef1bf7b,0x3f62be48,0xbe953f55,0xbf75bf0e,0xbe48bf80,0x3f7b8000,0xbf7b0000,0xbe48bf80,0x3f0e3f6d,0xbf553ec4,0x3f55bec4,0x3f0e3f6d,
0xbf55bf35,0x3f0ebf35,0xbf0e3f35,0xbf55bf35,0x3f7b3ec4,0xbe483f6d,0x3e48bf6d,0x3f7b3ec4,0x3f7f0000,0x3dc93f80,0x3f22bf35,0x3f463f35,
0xbf753e48,0xbe95bf7b,0xbef13f55,0xbf62bf0e,0x3f62bec4,0x3ef13f6d,0x3e95bf6d,0x3f753ec4,0xbf463f0e,0xbf22bf55,0xbdc93f7b,0xbf7fbe48,
0x3f80,0xbf808000,0x3f80,0xbf808000,0xbf80,0x3f808000,0xbf80,0x3f808000,0x3f80,0xbf808000,0x3f80,0xbf808000,
0xbf80,0x3f808000,0xbf80,0x3f808000,0xbf7f0000,0x3dc9bf80,0xbf22bf35,0x3f46bf35,0x3f753e48,0xbe953f7b,0x3ef13f55,0xbf623f0e,
0xbf62bec4,0x3ef1bf6d,0xbe95bf6d,0x3f75bec4,0x3f463f0e,0xbf223f55,0x3dc93f7b,0xbf7f3e48,0x3e48bf80,0x3f7b8000,0x3f7b0000,0xbe483f80,
0xbf0e3f6d,0xbf55bec4,0xbf55bec4,0x3f0ebf6d,0x3f55bf35,0x3f0e3f35,0x3f0e3f35,0xbf553f35,0xbf7b3ec4,0xbe48bf6d,0xbe48bf6d,0x3f7bbec4,
0x3f750000,0xbe953f80,0xbf623f35,0xbef1bf35,0xbf22bf0e,0x3f46bf55,0x3f7fbe48,0xbdc93f7b,0x3dc93f6d,0xbf7f3ec4,0xbf46bec4,0x3f22bf6d,
0x3ef1bf7b,0x3f623e48,0x3e953f55,0xbf753f0e,0xbec43f80,0xbf6d8000,0x3ec4bf80,0x3f6d8000,0x3f6dbf35,0x3ec43f35,0xbf6d3f35,0xbec4bf35,
0xbf6d0000,0x3ec4bf80,0x3f6d0000,0xbec43f80,0x3ec43f35,0xbf6d3f35,0xbec4bf35,0x3f6dbf35,0xbf620000,0x3ef1bf80,0x3e953f35,0xbf753f35,
0x3dc93f55,0xbf7f3f0e,0x3f22bf7b,0x3f463e48,0x3f46bf6d,0x3f223ec4,0xbf7f3ec4,0x3dc9bf6d,0xbf753e48,0x3e95bf7b,0x3ef13f0e,0xbf623f55,
0x3f0ebf80,0x3f558000,0xbf550000,0x3f0ebf80,0xbf7b3ec4,0x3e48bf6d,0xbe483f6d,0xbf7b3ec4,0x3e483f35,0xbf7b3f35,0x3f7bbf35,0x3e483f35,
0x3f55bf6d,0x3f0e3ec4,0xbf0ebec4,0x3f55bf6d,0x3f460000,0xbf223f80,0x3f7fbf35,0x3dc93f35,0x3ef1bf7b,0x3f62be48,0xbe95bf0e,0x3f75bf55,
0xbf753ec4,0x3e95bf6d,0xbf623f6d,0xbef1bec4,0xbdc93f55,0xbf7f3f0e,0x3f223e48,0xbf463f7b,0xbf353f80,0xbf358000,0xbf353f80,0xbf358000,
0x3f350000,0xbf353f80,0x3f350000,0xbf353f80,0x3f35bf80,0x3f358000,0x3f35bf80,0x3f358000,0xbf350000,0x3f35bf80,0xbf350000,0x3f35bf80,
0xbf220000,0x3f46bf80,0x3dc9bf35,0x3f7fbf35,0xbf623f7b,0xbef1be48,0xbf753f0e,0x3e95bf55,0x3e953ec4,0xbf753f6d,0xbef13f6d,0xbf623ec4,
0x3f7fbf55,0x3dc93f0e,0x3f46be48,0xbf223f7b,0x3f55bf80,0x3f0e8000,0x3f0e0000,0xbf553f80,0xbe48bec4,0x3f7bbf6d,0x3f7bbf6d,0x3e483ec4,
0xbf7b3f35,0x3e48bf35,0x3e48bf35,0x3f7bbf35,0xbf0e3f6d,0xbf553ec4,0xbf553ec4,0x3f0ebf6d,0x3ef10000,0xbf623f80,0xbf753f35,0x3e95bf35,
0x3f7fbf55,0xbdc93f0e,0xbf463f7b,0xbf223e48,0x3f22bf6d,0x3f46bec4,0x3dc93ec4,0xbf7f3f6d,0xbe95be48,0x3f75bf7b,0x3f62bf0e,0xbef13f55,
0xbf6d3f80,0xbec48000,0x3f6dbf80,0x3ec48000,0xbec43f35,0xbf6d3f35,0x3ec4bf35,0x3f6dbf35,0x3ec40000,0xbf6d3f80,0xbec40000,0x3f6dbf80,
0x3f6dbf35,0xbec43f35,0xbf6d3f35,0x3ec4bf35,0xbe950000,0x3f75bf80,0xbef13f35,0xbf623f35,0xbf463f0e,0x3f22bf55,0x3dc93e48,0xbf7f3f7b,
0xbf7f3f6d,0x3dc9bec4,0x3f22bec4,0xbf463f6d,0xbf623f7b,0xbef13e48,0x3f75bf55,0xbe953f0e,0x3f7bbf80,0x3e488000,0xbe480000,0x3f7bbf80,
0x3f55bf6d,0x3f0ebec4,0xbf0e3ec4,0x3f55bf6d,0x3f0ebf35,0x3f55bf35,0xbf553f35,0x3f0ebf35,0x3e48bec4,0x3f7bbf6d,0xbf7b3f6d,0x3e48bec4,
0x3dc90000,0xbf7f3f80,0x3f46bf35,0xbf223f35,0x3e95be48,0xbf753f7b,0x3f62bf55,0xbef13f0e,0x3ef1bec4,0xbf623f6d,0x3f75bf6d,0xbe953ec4,
0x3f22bf0e,0xbf463f55,0x3f7fbf7b,0xbdc93e48,0x3f803f80,0xbf803f80,0x3f803f80,0xbf803f80,0x3f803f80,0xbf803f80,0x3f803f80,0xbf803f80,
0x3f803f80,0xbf803f80,0x3f803f80,0xbf803f80,0x3f803f80,0xbf803f80,0x3f803f80,0xbf803f80,0xbf7fbf80,0x3dc98000,0xbf22bf35,0x3f463f35,
0xbf75bf7b,0x3e953e48,0xbef1bf0e,0x3f623f55,0xbf62bf6d,0x3ef13ec4,0xbe95bec4,0x3f753f6d,0xbf46bf55,0x3f223f0e,0xbdc9be48,0x3f7f3f7b,
0x3f7b3f80,0xbe488000,0xbe480000,0xbf7bbf80,0x3f553f6d,0xbf0ebec4,0xbf0ebec4,0xbf55bf6d,0x3f0e3f35,0xbf55bf35,0xbf55bf35,0xbf0ebf35,
0x3e483ec4,0xbf7bbf6d,0xbf7bbf6d,0xbe48bec4,0xbf75bf80,0x3e958000,0x3f623f35,0x3ef13f35,0xbf22bf55,0x3f463f0e,0x3f7f3f7b,0xbdc93e48,
0xbdc9bec4,0x3f7f3f6d,0x3f463f6d,0xbf22bec4,0x3ef13e48,0x3f623f7b,0x3e953f0e,0xbf75bf55,0x3f6d3f80,0xbec48000,0xbf6dbf80,0x3ec48000,
0x3ec43f35,0xbf6dbf35,0xbec4bf35,0x3f6d3f35,0xbec40000,0xbf6dbf80,0x3ec40000,0x3f6d3f80,0xbf6dbf35,0xbec4bf35,0x3f6d3f35,0x3ec43f35,
0xbf62bf80,0x3ef18000,0x3e953f35,0xbf75bf35,0xbdc9bf0e,0x3f7f3f55,0xbf22be48,0xbf46bf7b,0x3f463ec4,0x3f223f6d,0xbf7fbf6d,0x3dc9bec4,
0x3f753f7b,0xbe953e48,0xbef1bf55,0x3f623f0e,0x3f553f80,0xbf0e8000,0x3f0e0000,0x3f553f80,0xbe483ec4,0xbf7bbf6d,0x3f7b3f6d,0xbe483ec4,
0xbf7bbf35,0xbe48bf35,0x3e483f35,0xbf7bbf35,0xbf0ebf6d,0x3f553ec4,0xbf55bec4,0xbf0ebf6d,0xbf46bf80,0x3f228000,0xbf7fbf35,0xbdc9bf35,
0x3ef1be48,0x3f623f7b,0xbe95bf55,0x3f753f0e,0x3f753f6d,0xbe953ec4,0x3f623ec4,0x3ef13f6d,0xbdc93f0e,0xbf7fbf55,0x3f223f7b,0xbf46be48,
0x3f353f80,0xbf358000,0x3f353f80,0xbf358000,0xbf350000,0xbf35bf80,0xbf350000,0xbf35bf80,0xbf35bf80,0x3f358000,0xbf35bf80,0x3f358000,
0x3f350000,0x3f353f80,0x3f350000,0x3f353f80,0xbf22bf80,0x3f468000,0x3dc9bf35,0x3f7f3f35,0x3f623e48,0x3ef13f7b,0x3f753f55,0xbe953f0e,
0x3e953f6d,0xbf75bec4,0xbef13ec4,0xbf62bf6d,0xbf7fbf0e,0xbdc9bf55,0xbf46bf7b,0x3f22be48,0x3f0e3f80,0xbf558000,0xbf550000,0xbf0ebf80,
0xbf7bbec4,0xbe48bf6d,0xbe48bf6d,0x3f7b3ec4,0x3e48bf35,0x3f7b3f35,0x3f7b3f35,0xbe483f35,0x3f553f6d,0xbf0e3ec4,0xbf0e3ec4,0xbf55bf6d,
0xbef1bf80,0x3f628000,0x3f753f35,0xbe953f35,0x3f7f3f0e,0xbdc93f55,0xbf463e48,0xbf22bf7b,0xbf223ec4,0xbf46bf6d,0xbdc9bf6d,0x3f7f3ec4,
0xbe95bf7b,0x3f753e48,0x3f623f55,0xbef13f0e,0x3ec43f80,0xbf6d8000,0xbec4bf80,0x3f6d8000,0xbf6dbf35,0x3ec4bf35,0x3f6d3f35,0xbec43f35,
0x3f6d0000,0x3ec43f80,0xbf6d0000,0xbec4bf80,0xbec43f35,0xbf6dbf35,0x3ec4bf35,0x3f6d3f35,0xbe95bf80,0x3f758000,0xbef13f35,0xbf62bf35,
0x3f463f55,0xbf223f0e,0xbdc9bf7b,0x3f7f3e48,0xbf7fbec4,0x3dc9bf6d,0x3f223f6d,0xbf463ec4,0x3f62be48,0x3ef13f7b,0xbf75bf0e,0x3e95bf55,
0x3e483f80,0xbf7b8000,0x3f7b0000,0x3e483f80,0xbf0ebf6d,0x3f55bec4,0xbf553ec4,0xbf0ebf6d,0x3f553f35,0xbf0e3f35,0x3f0ebf35,0x3f553f35,
0xbf7bbec4,0x3e48bf6d,0xbe483f6d,0xbf7bbec4,0xbdc9bf80,0x3f7f8000,0xbf46bf35,0x3f22bf35,0x3e953f7b,0xbf753e48,0x3f623f0e,0xbef13f55,
0xbef1bf6d,0x3f62bec4,0xbf75bec4,0x3e95bf6d,0x3f223f55,0xbf463f0e,0x3f7f3e48,0xbdc93f7b,0x3f80,0xbf808000,0x3f80,0xbf808000,
0xbf80,0x3f808000,0xbf80,0x3f808000,0x3f80,0xbf808000,0x3f80,0xbf808000,0xbf80,0x3f808000,0xbf80,0x3f808000,
0x3dc9bf80,0x3f7f8000,0x3f46bf35,0x3f223f35,0xbe953f7b,0xbf75be48,0xbf623f0e,0xbef1bf55,0x3ef1bf6d,0x3f623ec4,0x3f75bec4,0x3e953f6d,
0xbf223f55,0xbf46bf0e,0xbf7f3e48,0xbdc9bf7b,0xbe483f80,0xbf7b8000,0xbf7b0000,0x3e48bf80,0x3f0ebf6d,0x3f553ec4,0x3f553ec4,0xbf0e3f6d,
0xbf553f35,0xbf0ebf35,0xbf0ebf35,0x3f55bf35,0x3f7bbec4,0x3e483f6d,0x3e483f6d,0xbf7b3ec4,0x3e95bf80,0x3f758000,0x3ef13f35,0xbf623f35,
0xbf463f55,0xbf22bf0e,0x3dc9bf7b,0x3f7fbe48,0x3f7fbec4,0x3dc93f6d,0xbf223f6d,0xbf46bec4,0xbf62be48,0x3ef1bf7b,0x3f75bf0e,0x3e953f55,
0xbec43f80,0xbf6d8000,0x3ec4bf80,0x3f6d8000,0x3f6dbf35,0x3ec43f35,0xbf6d3f35,0xbec4bf35,0xbf6d0000,0x3ec4bf80,0x3f6d0000,0xbec43f80,
0x3ec43f35,0xbf6d3f35,0xbec4bf35,0x3f6dbf35,0x3ef1bf80,0x3f628000,0xbf753f35,0xbe95bf35,0xbf7f3f0e,0xbdc9bf55,0x3f463e48,0xbf223f7b,
0x3f223ec4,0xbf463f6d,0x3dc9bf6d,0x3f7fbec4,0x3e95bf7b,0x3f75be48,0xbf623f55,0xbef1bf0e,0xbf0e3f80,0xbf558000,0x3f550000,0xbf0e3f80,
0x3f7bbec4,0xbe483f6d,0x3e48bf6d,0x3f7bbec4,0xbe48bf35,0x3f7bbf35,0xbf7b3f35,0xbe48bf35,0xbf553f6d,0xbf0ebec4,0x3f0e3ec4,0xbf553f6d,
0x3f22bf80,0x3f468000,0xbdc9bf35,0x3f7fbf35,0xbf623e48,0x3ef1bf7b,0xbf753f55,0xbe95bf0e,0xbe953f6d,0xbf753ec4,0x3ef13ec4,0xbf623f6d,
0x3f7fbf0e,0xbdc93f55,0x3f46bf7b,0x3f223e48,0xbf353f80,0xbf358000,0xbf353f80,0xbf358000,0x3f350000,0xbf353f80,0x3f350000,0xbf353f80,
0x3f35bf80,0x3f358000,0x3f35bf80,0x3f358000,0xbf350000,0x3f35bf80,0xbf350000,0x3f35bf80,0x3f46bf80,0x3f228000,0x3f7fbf35,0xbdc93f35,
0xbef1be48,0x3f62bf7b,0x3e95bf55,0x3f75bf0e,0xbf753f6d,0xbe95bec4,0xbf623ec4,0x3ef1bf6d,0x3dc93f0e,0xbf7f3f55,0xbf223f7b,0xbf463e48,
0xbf553f80,0xbf0e8000,0xbf0e0000,0x3f55bf80,0x3e483ec4,0xbf7b3f6d,0xbf7b3f6d,0xbe48bec4,0x3f7bbf35,0xbe483f35,0xbe483f35,0xbf7b3f35,
0x3f0ebf6d,0x3f55bec4,0x3f55bec4,0xbf0e3f6d,0x3f62bf80,0x3ef18000,0xbe953f35,0xbf753f35,0x3dc9bf0e,0x3f7fbf55,0x3f22be48,0xbf463f7b,
0xbf463ec4,0x3f22bf6d,0x3f7fbf6d,0x3dc93ec4,0xbf753f7b,0xbe95be48,0x3ef1bf55,0x3f62bf0e,0xbf6d3f80,0xbec48000,0x3f6dbf80,0x3ec48000,
0xbec43f35,0xbf6d3f35,0x3ec4bf35,0x3f6dbf35,0x3ec40000,0xbf6d3f80,0xbec40000,0x3f6dbf80,0x3f6dbf35,0xbec43f35,0xbf6d3f35,0x3ec4bf35,
0x3f75bf80,0x3e958000,0xbf623f35,0x3ef1bf35,0x3f22bf55,0x3f46bf0e,0xbf7f3f7b,0xbdc9be48,0x3dc9bec4,0x3f7fbf6d,0xbf463f6d,0xbf223ec4,
0xbef13e48,0x3f62bf7b,0xbe953f0e,0xbf753f55,0xbf7b3f80,0xbe488000,0x3e480000,0xbf7b3f80,0xbf553f6d,0xbf0e3ec4,0x3f0ebec4,0xbf553f6d,
0xbf0e3f35,0xbf553f35,0x3f55bf35,0xbf0e3f35,0xbe483ec4,0xbf7b3f6d,0x3f7bbf6d,0xbe483ec4,0x3f7fbf80,0x3dc98000,0x3f22bf35,0x3f46bf35,
0x3f75bf7b,0x3e95be48,0x3ef1bf0e,0x3f62bf55,0x3f62bf6d,0x3ef1bec4,0x3e95bec4,0x3f75bf6d,0x3f46bf55,0x3f22bf0e,0x3dc9be48,0x3f7fbf7b,
0x3f803f80,0xbf803f80,0x3f803f80,0xbf803f80,0x3f803f80,0xbf803f80,0x3f803f80,0xbf803f80,0x3f803f80,0xbf803f80,0x3f803f80,0xbf803f80,
0x3f803f80,0xbf803f80,0x3f803f80,0xbf803f80,0x3dc90000,0x3f7f3f80,0x3f463f35,0x3f223f35,0x3e953e48,0x3f753f7b,0x3f623f55,0x3ef13f0e,
0x3ef13ec4,0x3f623f6d,0x3f753f6d,0x3e953ec4,0x3f223f0e,0x3f463f55,0x3f7f3f7b,0x3dc93e48,0xbf7bbf80,0x3e488000,0x3e480000,0x3f7b3f80,
0xbf55bf6d,0x3f0e3ec4,0x3f0e3ec4,0x3f553f6d,0xbf0ebf35,0x3f553f35,0x3f553f35,0x3f0e3f35,0xbe48bec4,0x3f7b3f6d,0x3f7b3f6d,0x3e483ec4,
0xbe950000,0xbf75bf80,0xbef1bf35,0x3f623f35,0xbf46bf0e,0xbf22bf55,0x3dc9be48,0x3f7f3f7b,0xbf7fbf6d,0xbdc9bec4,0x3f223ec4,0x3f463f6d,
0xbf62bf7b,0x3ef13e48,0x3f753f55,0x3e953f0e,0x3f6d3f80,0xbec48000,0xbf6dbf80,0x3ec48000,0x3ec43f35,0xbf6dbf35,0xbec4bf35,0x3f6d3f35,
0xbec40000,0xbf6dbf80,0x3ec40000,0x3f6d3f80,0xbf6dbf35,0xbec4bf35,0x3f6d3f35,0x3ec43f35,0x3ef10000,0x3f623f80,0xbf75bf35,0xbe95bf35,
0x3f7f3f55,0x3dc93f0e,0xbf46bf7b,0x3f223e48,0x3f223f6d,0xbf46bec4,0x3dc9bec4,0x3f7f3f6d,0xbe953e48,0xbf75bf7b,0x3f623f0e,0x3ef13f55,
0xbf55bf80,0x3f0e8000,0xbf0e0000,0xbf55bf80,0x3e48bec4,0x3f7b3f6d,0xbf7bbf6d,0x3e48bec4,0x3f7b3f35,0x3e483f35,0xbe48bf35,0x3f7b3f35,
0x3f0e3f6d,0xbf55bec4,0x3f553ec4,0x3f0e3f6d,0xbf220000,0xbf46bf80,0x3dc93f35,0xbf7fbf35,0xbf62bf7b,0x3ef1be48,0xbf75bf0e,0xbe95bf55,
0x3e95bec4,0x3f753f6d,0xbef1bf6d,0x3f623ec4,0x3f7f3f55,0xbdc93f0e,0x3f463e48,0x3f223f7b,0x3f353f80,0xbf358000,0x3f353f80,0xbf358000,
0xbf350000,0xbf35bf80,0xbf350000,0xbf35bf80,0xbf35bf80,0x3f358000,0xbf35bf80,0x3f358000,0x3f350000,0x3f353f80,0x3f350000,0x3f353f80,
0x3f460000,0x3f223f80,0x3f7f3f35,0xbdc93f35,0x3ef13f7b,0xbf62be48,0xbe953f0e,0xbf75bf55,0xbf75bec4,0xbe95bf6d,0xbf62bf6d,0x3ef1bec4,
0xbdc9bf55,0x3f7f3f0e,0x3f22be48,0x3f463f7b,0xbf0ebf80,0x3f558000,0x3f550000,0x3f0e3f80,0x3f7b3ec4,0x3e483f6d,0x3e483f6d,0xbf7bbec4,
0xbe483f35,0xbf7bbf35,0xbf7bbf35,0x3e48bf35,0xbf55bf6d,0x3f0ebec4,0x3f0ebec4,0x3f553f6d,0xbf620000,0xbef1bf80,0x3e95bf35,0x3f753f35,
0x3dc9bf55,0x3f7f3f0e,0x3f223f7b,0xbf463e48,0x3f463f6d,0xbf223ec4,0xbf7fbec4,0xbdc9bf6d,0xbf75be48,0xbe95bf7b,0x3ef1bf0e,0x3f623f55,
0x3ec43f80,0xbf6d8000,0xbec4bf80,0x3f6d8000,0xbf6dbf35,0x3ec4bf35,0x3f6d3f35,0xbec43f35,0x3f6d0000,0x3ec43f80,0xbf6d0000,0xbec4bf80,
0xbec43f35,0xbf6dbf35,0x3ec4bf35,0x3f6d3f35,0x3f750000,0x3e953f80,0xbf62bf35,0x3ef1bf35,0xbf223f0e,0xbf46bf55,0x3f7f3e48,0x3dc93f7b,
0x3dc9bf6d,0x3f7f3ec4,0xbf463ec4,0xbf22bf6d,0x3ef13f7b,0xbf623e48,0x3e95bf55,0x3f753f0e,0xbe48bf80,0x3f7b8000,0xbf7b0000,0xbe48bf80,
0x3f0e3f6d,0xbf553ec4,0x3f55bec4,0x3f0e3f6d,0xbf55bf35,0x3f0ebf35,0xbf0e3f35,0xbf55bf35,0x3f7b3ec4,0xbe483f6d,0x3e48bf6d,0x3f7b3ec4,
0xbf7f0000,0xbdc9bf80,0xbf223f35,0xbf46bf35,0x3f75be48,0x3e953f7b,0x3ef1bf55,0x3f623f0e,0xbf623ec4,0xbef1bf6d,0xbe953f6d,0xbf75bec4,
0x3f46bf0e,0x3f223f55,0x3dc9bf7b,0x3f7f3e48,0x3f80,0xbf808000,0x3f80,0xbf808000,0xbf80,0x3f808000,0xbf80,0x3f808000,
0x3f80,0xbf808000,0x3f80,0xbf808000,0xbf80,0x3f808000,0xbf80,0x3f808000,0x3f7f0000,0xbdc93f80,0x3f223f35,0xbf463f35,
0xbf75be48,0x3e95bf7b,0xbef1bf55,0x3f62bf0e,0x3f623ec4,0xbef13f6d,0x3e953f6d,0xbf753ec4,0xbf46bf0e,0x3f22bf55,0xbdc9bf7b,0x3f7fbe48,
0x3e48bf80,0x3f7b8000,0x3f7b0000,0xbe483f80,0xbf0e3f6d,0xbf55bec4,0xbf55bec4,0x3f0ebf6d,0x3f55bf35,0x3f0e3f35,0x3f0e3f35,0xbf553f35,
0xbf7b3ec4,0xbe48bf6d,0xbe48bf6d,0x3f7bbec4,0xbf750000,0x3e95bf80,0x3f62bf35,0x3ef13f35,0x3f223f0e,0xbf463f55,0xbf7f3e48,0x3dc9bf7b,
0xbdc9bf6d,0x3f7fbec4,0x3f463ec4,0xbf223f6d,0xbef13f7b,0xbf62be48,0xbe95bf55,0x3f75bf0e,0xbec43f80,0xbf6d8000,0x3ec4bf80,0x3f6d8000,
0x3f6dbf35,0x3ec43f35,0xbf6d3f35,0xbec4bf35,0xbf6d0000,0x3ec4bf80,0x3f6d0000,0xbec43f80,0x3ec43f35,0xbf6d3f35,0xbec4bf35,0x3f6dbf35,
0x3f620000,0xbef13f80,0xbe95bf35,0x3f75bf35,0xbdc9bf55,0x3f7fbf0e,0xbf223f7b,0xbf46be48,0xbf463f6d,0xbf22bec4,0x3f7fbec4,0xbdc93f6d,
0x3f75be48,0xbe953f7b,0xbef1bf0e,0x3f62bf55,0x3f0ebf80,0x3f558000,0xbf550000,0x3f0ebf80,0xbf7b3ec4,0x3e48bf6d,0xbe483f6d,0xbf7b3ec4,
0x3e483f35,0xbf7b3f35,0x3f7bbf35,0x3e483f35,0x3f55bf6d,0x3f0e3ec4,0xbf0ebec4,0x3f55bf6d,0xbf460000,0x3f22bf80,0xbf7f3f35,0xbdc9bf35,
0xbef13f7b,0xbf623e48,0x3e953f0e,0xbf753f55,0x3f75bec4,0xbe953f6d,0x3f62bf6d,0x3ef13ec4,0x3dc9bf55,0x3f7fbf0e,0xbf22be48,0x3f46bf7b,
0xbf353f80,0xbf358000,0xbf353f80,0xbf358000,0x3f350000,0xbf353f80,0x3f350000,0xbf353f80,0x3f35bf80,0x3f358000,0x3f35bf80,0x3f358000,
0xbf350000,0x3f35bf80,0xbf350000,0x3f35bf80,0x3f220000,0xbf463f80,0xbdc93f35,0xbf7f3f35,0x3f62bf7b,0x3ef13e48,0x3f75bf0e,0xbe953f55,
0xbe95bec4,0x3f75bf6d,0x3ef1bf6d,0x3f62bec4,0xbf7f3f55,0xbdc9bf0e,0xbf463e48,0x3f22bf7b,0x3f55bf80,0x3f0e8000,0x3f0e0000,0xbf553f80,
0xbe48bec4,0x3f7bbf6d,0x3f7bbf6d,0x3e483ec4,0xbf7b3f35,0x3e48bf35,0x3e48bf35,0x3f7bbf35,0xbf0e3f6d,0xbf553ec4,0xbf553ec4,0x3f0ebf6d,
0xbef10000,0x3f62bf80,0x3f75bf35,0xbe953f35,0xbf7f3f55,0x3dc9bf0e,0x3f46bf7b,0x3f22be48,0xbf223f6d,0xbf463ec4,0xbdc9bec4,0x3f7fbf6d,
0x3e953e48,0xbf753f7b,0xbf623f0e,0x3ef1bf55,0xbf6d3f80,0xbec48000,0x3f6dbf80,0x3ec48000,0xbec43f35,0xbf6d3f35,0x3ec4bf35,0x3f6dbf35,
0x3ec40000,0xbf6d3f80,0xbec40000,0x3f6dbf80,0x3f6dbf35,0xbec43f35,0xbf6d3f35,0x3ec4bf35,0x3e950000,0xbf753f80,0x3ef1bf35,0x3f62bf35,
0x3f46bf0e,0xbf223f55,0xbdc9be48,0x3f7fbf7b,0x3f7fbf6d,0xbdc93ec4,0xbf223ec4,0x3f46bf6d,0x3f62bf7b,0x3ef1be48,0xbf753f55,0x3e95bf0e,
0x3f7bbf80,0x3e488000,0xbe480000,0x3f7bbf80,0x3f55bf6d,0x3f0ebec4,0xbf0e3ec4,0x3f55bf6d,0x3f0ebf35,0x3f55bf35,0xbf553f35,0x3f0ebf35,
0x3e48bec4,0x3f7bbf6d,0xbf7b3f6d,0x3e48bec4,0xbdc90000,0x3f7fbf80,0xbf463f35,0x3f22bf35,0xbe953e48,0x3f75bf7b,0xbf623f55,0x3ef1bf0e,
0xbef13ec4,0x3f62bf6d,0xbf753f6d,0x3e95bec4,0xbf223f0e,0x3f46bf55,0xbf7f3f7b,0x3dc9be48,0x3f803f80,0xbf353f35,0x3f803f80,0xbf353f35,
0x3f803f80,0xbf353f35,0x3f803f80,0xbf353f35,0x3f803f80,0xbf353f35,0x3f803f80,0xbf353f35,0x3f803f80,0xbf353f35,0x3f803f80,0xbf353f35,
0x3f7e3f80,0xbdfbbcc9,0x3f1d3f31,0xbf4abf39,0x3f733f7a,0xbea1be60,0x3ee63f09,0xbf65bf58,0x3f5f3f6a,0xbefcbecf,0x3e893eb8,0xbf77bf6f,
0x3f423f51,0xbf27bf13,0x3d973e2f,0xbf7fbf7c,0x3f783f80,0xbe79bd49,0xbe79bd49,0xbf78bf80,0x3f4e3f67,0xbf18bedb,0xbf18bedb,0xbf4ebf67,
0x3f043f2c,0xbf5cbf3e,0xbf5cbf3e,0xbf04bf2c,0x3e163eac,0xbf7dbf71,0xbf7dbf71,0xbe16beac,0x3f6f3f7f,0xbeb8bd97,0xbf6abf42,0xbecfbf27,
0x3f133f4a,0xbf51bf1d,0xbf7cbf7e,0x3e2fbdfb,0x3cc93ea1,0xbf80bf73,0xbf39bf65,0x3f313ee6,0xbf09be89,0xbf58bf77,0xbe60befc,0x3f7a3f5f,
0x3f623f7f,0xbef1bdc9,0xbf62bf7f,0x3ef13dc9,0x3e953f22,0xbf75bf46,0xbe95bf22,0x3f753f46,0xbef1bdc9,0xbf62bf7f,0x3ef13dc9,0x3f623f7f,
0xbf75bf46,0xbe95bf22,0x3f753f46,0x3e953f22,0x3f513f7e,0xbf13bdfb,0xbe2fbf1d,0x3f7c3f4a,0xbcc93ee6,0xbf80bf65,0x3f393ea1,0x3f313f73,
0xbf58befc,0xbf09bf5f,0x3f7a3f77,0xbe603e89,0xbf6abf7f,0x3ecfbd97,0x3eb83f42,0xbf6fbf27,0x3f3e3f7d,0xbf2cbe16,0x3f2c3e16,0x3f3e3f7d,
0xbeac3e79,0xbf71bf78,0x3f713f78,0xbeac3e79,0xbf80bf4e,0xbd49bf18,0x3d493f18,0xbf80bf4e,0xbedbbf5c,0x3f673f04,0xbf67bf04,0xbedbbf5c,
0x3f273f7c,0xbf42be2f,0x3f7f3f51,0xbd973f13,0xbf1d3cc9,0xbf4abf80,0x3dfb3f39,0xbf7ebf31,0xbf65bf7a,0x3ee6be60,0xbf73bf09,0xbea1bf58,
0x3e89becf,0x3f773f6a,0xbefcbf6f,0x3f5f3eb8,0x3f0e3f7b,0xbf55be48,0x3f0e3f7b,0xbf55be48,0xbf55be48,0xbf0ebf7b,0xbf55be48,0xbf0ebf7b,
0xbf0ebf7b,0x3f553e48,0xbf0ebf7b,0x3f553e48,0x3f553e48,0x3f0e3f7b,0x3f553e48,0x3f0e3f7b,0x3ee63f7a,0xbf65be60,0xbea13f09,0xbf73bf58,
0xbf77becf,0xbe89bf6a,0xbf5fbf6f,0x3efcbeb8,0xbd97bf51,0x3f7f3f13,0x3f27be2f,0x3f423f7c,0x3f7e3f39,0xbdfb3f31,0x3f1d3f80,0xbf4abcc9,
0x3eac3f78,0xbf71be79,0xbf71be79,0xbeacbf78,0xbf80bf18,0x3d49bf4e,0x3d49bf4e,0x3f803f18,0x3edbbf04,0x3f673f5c,0x3f673f5c,0xbedb3f04,
0x3f2c3f7d,0xbf3e3e16,0xbf3e3e16,0xbf2cbf7d,0x3e603f77,0xbf7abe89,0xbf58bf5f,0x3f09befc,0xbf6fbf42,0x3eb8bf27,0x3f6a3d97,0x3ecf3f7f,
0x3f51bdfb,0x3f133f7e,0xbe2f3f4a,0xbf7cbf1d,0x3cc93f65,0xbf80bee6,0xbf39bf73,0x3f31bea1,0x3dc93f75,0xbf7fbe95,0xbdc9bf75,0x3f7f3e95,
0xbf46bf62,0x3f22bef1,0x3f463f62,0xbf223ef1,0x3f7f3e95,0x3dc93f75,0xbf7fbe95,0xbdc9bf75,0xbf223ef1,0xbf46bf62,0x3f22bef1,0x3f463f62,
0xbcc93f73,0xbf80bea1,0x3f39bee6,0x3f313f65,0xbf09bf77,0x3f58be89,0xbe603f5f,0xbf7abefc,0x3f6a3f27,0xbecf3f42,0xbeb8bf7f,0x3f6fbd97,
0xbf7cbdfb,0xbe2fbf7e,0x3f513f4a,0xbf133f1d,0xbe163f71,0xbf7dbeac,0x3f7d3eac,0xbe163f71,0xbe79bf80,0x3f78bd49,0xbf783d49,0xbe79bf80,
0x3f183f67,0xbf4e3edb,0x3f4ebedb,0x3f183f67,0xbf5cbf2c,0x3f04bf3e,0xbf043f3e,0xbf5cbf2c,0xbe893f6f,0xbf77beb8,0x3efc3f6a,0xbf5f3ecf,
0x3d97bf7c,0x3f7f3e2f,0xbf27bf51,0x3f42bf13,0x3dfb3f80,0xbf7e3cc9,0x3f4a3f31,0xbf1d3f39,0xbea1bf7a,0x3f73be60,0xbf65bf09,0x3ee6bf58,
0xbec43f6d,0xbf6dbec4,0xbec43f6d,0xbf6dbec4,0x3ec4bf6d,0x3f6d3ec4,0x3ec4bf6d,0x3f6d3ec4,0xbec43f6d,0xbf6dbec4,0xbec43f6d,0xbf6dbec4,
0x3ec4bf6d,0x3f6d3ec4,0x3ec4bf6d,0x3f6d3ec4,0xbefc3f6a,0xbf5fbecf,0xbf773eb8,0xbe89bf6f,0x3f27bf51,0x3f423f13,0x3f7fbe2f,0x3d973f7c,
0xbf4a3f31,0xbf1dbf39,0xbf7ebcc9,0x3dfbbf80,0x3f65bf09,0x3ee63f58,0x3f733e60,0xbea13f7a,0xbf183f67,0xbf4ebedb,0xbf4ebedb,0x3f18bf67,
0x3f5cbf2c,0x3f043f3e,0x3f043f3e,0xbf5c3f2c,0xbf7d3eac,0xbe16bf71,0xbe16bf71,0x3f7dbeac,0x3f783d49,0xbe793f80,0xbe793f80,0xbf78bd49,
0xbf313f65,0xbf39bee6,0xbcc9bf73,0x3f80bea1,0x3f7abefc,0x3e603f5f,0xbf093f77,0xbf58be89,0xbf6fbd97,0x3eb8bf7f,0x3f6abf27,0x3ecf3f42,
0x3f133f1d,0xbf513f4a,0xbf7c3dfb,0x3e2fbf7e,0xbf463f62,0xbf22bef1,0x3f46bf62,0x3f223ef1,0x3f7fbe95,0xbdc93f75,0xbf7f3e95,0x3dc9bf75,
0xbf22bef1,0x3f46bf62,0x3f223ef1,0xbf463f62,0xbdc93f75,0xbf7f3e95,0x3dc9bf75,0x3f7fbe95,0xbf583f5f,0xbf09befc,0x3f7abe89,0xbe603f77,
0x3f6abd97,0xbecf3f7f,0xbeb8bf27,0x3f6fbf42,0xbe2fbf4a,0x3f7cbf1d,0xbf133f7e,0xbf51bdfb,0xbf393f73,0xbf31bea1,0x3f80bee6,0xbcc93f65,
0xbf673f5c,0xbedbbf04,0x3edb3f04,0xbf673f5c,0x3f3e3e16,0xbf2c3f7d,0x3f2cbf7d,0x3f3e3e16,0x3eacbf78,0x3f71be79,0xbf713e79,0x3eacbf78,
0xbf803f18,0xbd49bf4e,0x3d493f4e,0xbf803f18,0xbf733f58,0xbea1bf09,0xbee63f7a,0xbf653e60,0x3efc3eb8,0xbf5f3f6f,0x3f77becf,0xbe893f6a,
0x3f42bf7c,0x3f273e2f,0x3d97bf51,0x3f7fbf13,0xbf4a3cc9,0x3f1dbf80,0xbf7e3f39,0xbdfbbf31,0xbf7b3f55,0xbe48bf0e,0xbf7b3f55,0xbe48bf0e,
0x3e483f0e,0xbf7b3f55,0x3e483f0e,0xbf7b3f55,0x3f7bbf55,0x3e483f0e,0x3f7bbf55,0x3e483f0e,0xbe48bf0e,0x3f7bbf55,0xbe48bf0e,0x3f7bbf55,
0xbf7f3f51,0xbd97bf13,0xbf423e2f,0x3f27bf7c,0xbdfb3f39,0xbf7e3f31,0xbf4a3f80,0xbf1dbcc9,0x3f73bf09,0xbea13f58,0x3ee63e60,0xbf653f7a,
0x3efcbf6f,0x3f5fbeb8,0x3f77bf6a,0x3e893ecf,0xbf803f4e,0x3d49bf18,0x3d49bf18,0x3f80bf4e,0xbedb3f5c,0xbf673f04,0xbf673f04,0x3edbbf5c,
0x3f2cbe16,0xbf3e3f7d,0xbf3e3f7d,0xbf2c3e16,0x3f71bf78,0x3eac3e79,0x3eac3e79,0xbf713f78,0xbf7c3f4a,0x3e2fbf1d,0x3f51bf7e,0x3f13bdfb,
0xbf313f73,0xbf393ea1,0xbcc9bee6,0x3f80bf65,0x3e603e89,0xbf7a3f77,0xbf583efc,0x3f09bf5f,0x3f6fbf27,0xbeb83f42,0xbf6a3f7f,0xbecfbd97,
0xbf753f46,0x3e95bf22,0x3f75bf46,0xbe953f22,0xbf623f7f,0xbef13dc9,0x3f62bf7f,0x3ef1bdc9,0xbe953f22,0xbf753f46,0x3e95bf22,0x3f75bf46,
0x3ef1bdc9,0xbf623f7f,0xbef13dc9,0x3f62bf7f,0xbf6a3f42,0x3ecfbf27,0x3eb8bd97,0xbf6f3f7f,0xbf7c3f7e,0xbe2fbdfb,0x3f51bf1d,0xbf133f4a,
0xbf393f65,0xbf313ee6,0x3f80bf73,0xbcc93ea1,0xbe603efc,0xbf7a3f5f,0x3f58bf77,0x3f09be89,0xbf5c3f3e,0x3f04bf2c,0xbf043f2c,0xbf5c3f3e,
0xbf7d3f71,0x3e16beac,0xbe163eac,0xbf7d3f71,0xbf783f80,0xbe793d49,0x3e79bd49,0xbf783f80,0xbf4e3f67,0xbf183edb,0x3f18bedb,0xbf4e3f67,
0xbf4a3f39,0x3f1dbf31,0xbf7e3f80,0xbdfb3cc9,0xbf653f58,0x3ee6bf09,0xbf733f7a,0xbea13e60,0xbf773f6f,0x3e89beb8,0xbf5f3f6a,0xbefc3ecf,
0xbf7f3f7c,0x3d97be2f,0xbf423f51,0xbf273f13,0x3f803f80,0xbf353f35,0x3f803f80,0xbf353f35,0x3f803f80,0xbf353f35,0x3f803f80,0xbf353f35,
0x3f803f80,0xbf353f35,0x3f803f80,0xbf353f35,0x3f803f80,0xbf353f35,0x3f803f80,0xbf353f35,0xbdfbbcc9,0xbf7ebf80,0xbf4abf39,0xbf1dbf31,
0xbea1be60,0xbf73bf7a,0xbf65bf58,0xbee6bf09,0xbefcbecf,0xbf5fbf6a,0xbf77bf6f,0xbe89beb8,0xbf27bf13,0xbf42bf51,0xbf7fbf7c,0xbd97be2f,
0xbf78bf80,0x3e793d49,0x3e793d49,0x3f783f80,0xbf4ebf67,0x3f183edb,0x3f183edb,0x3f4e3f67,0xbf04bf2c,0x3f5c3f3e,0x3f5c3f3e,0x3f043f2c,
0xbe16beac,0x3f7d3f71,0x3f7d3f71,0x3e163eac,0x3eb83d97,0x3f6f3f7f,0x3ecf3f27,0xbf6abf42,0x3f513f1d,0x3f133f4a,0xbe2f3dfb,0xbf7cbf7e,
0x3f803f73,0x3cc93ea1,0xbf31bee6,0xbf39bf65,0x3f583f77,0xbf09be89,0xbf7abf5f,0xbe60befc,0x3f623f7f,0xbef1bdc9,0xbf62bf7f,0x3ef13dc9,
0x3e953f22,0xbf75bf46,0xbe95bf22,0x3f753f46,0xbef1bdc9,0xbf62bf7f,0x3ef13dc9,0x3f623f7f,0xbf75bf46,0xbe95bf22,0x3f753f46,0x3e953f22,
0xbf13bdfb,0xbf51bf7e,0x3f7c3f4a,0x3e2f3f1d,0xbf80bf65,0x3cc9bee6,0x3f313f73,0xbf39bea1,0xbf09bf5f,0x3f583efc,0xbe603e89,0xbf7abf77,
0x3ecfbd97,0x3f6a3f7f,0xbf6fbf27,0xbeb8bf42,0xbf3ebf7d,0x3f2c3e16,0xbf2cbe16,0xbf3ebf7d,0x3eacbe79,0x3f713f78,0xbf71bf78,0x3eacbe79,
0x3f803f4e,0x3d493f18,0xbd49bf18,0x3f803f4e,0x3edb3f5c,0xbf67bf04,0x3f673f04,0x3edb3f5c,0x3f423e2f,0x3f273f7c,0x3d97bf13,0x3f7f3f51,
0x3f4a3f80,0xbf1d3cc9,0x3f7e3f31,0x3dfb3f39,0xbee63e60,0xbf65bf7a,0x3ea13f58,0xbf73bf09,0xbf77bf6a,0x3e89becf,0xbf5fbeb8,0xbefcbf6f,
0x3f0e3f7b,0xbf55be48,0x3f0e3f7b,0xbf55be48,0xbf55be48,0xbf0ebf7b,0xbf55be48,0xbf0ebf7b,0xbf0ebf7b,0x3f553e48,0xbf0ebf7b,0x3f553e48,
0x3f553e48,0x3f0e3f7b,0x3f553e48,0x3f0e3f7b,0xbf65be60,0xbee6bf7a,0xbf73bf58,0x3ea1bf09,0xbe89bf6a,0x3f773ecf,0x3efcbeb8,0x3f5f3f6f,
0x3f7f3f13,0x3d973f51,0x3f423f7c,0xbf273e2f,0xbdfb3f31,0xbf7ebf39,0xbf4abcc9,0xbf1dbf80,0xbeacbf78,0x3f713e79,0x3f713e79,0x3eac3f78,
0x3f803f18,0xbd493f4e,0xbd493f4e,0xbf80bf18,0xbedb3f04,0xbf67bf5c,0xbf67bf5c,0x3edbbf04,0xbf2cbf7d,0x3f3ebe16,0x3f3ebe16,0x3f2c3f7d,
0x3f7a3e89,0x3e603f77,0xbf093efc,0xbf58bf5f,0xbeb83f27,0xbf6fbf42,0xbecfbf7f,0x3f6a3d97,0xbf13bf7e,0x3f51bdfb,0x3f7c3f1d,0xbe2f3f4a,
0x3f803ee6,0x3cc93f65,0xbf313ea1,0xbf39bf73,0x3dc93f75,0xbf7fbe95,0xbdc9bf75,0x3f7f3e95,0xbf46bf62,0x3f22bef1,0x3f463f62,0xbf223ef1,
0x3f7f3e95,0x3dc93f75,0xbf7fbe95,0xbdc9bf75,0xbf223ef1,0xbf46bf62,0x3f22bef1,0x3f463f62,0xbf80bea1,0x3cc9bf73,0x3f313f65,0xbf393ee6,
0x3f58be89,0x3f093f77,0xbf7abefc,0x3e60bf5f,0xbecf3f42,0xbf6abf27,0x3f6fbd97,0x3eb83f7f,0xbe2fbf7e,0x3f7c3dfb,0xbf133f1d,0xbf51bf4a,
0x3e16bf71,0x3f7d3eac,0xbf7dbeac,0x3e16bf71,0x3e793f80,0xbf783d49,0x3f78bd49,0x3e793f80,0xbf18bf67,0x3f4ebedb,0xbf4e3edb,0xbf18bf67,
0x3f5c3f2c,0xbf043f3e,0x3f04bf3e,0x3f5c3f2c,0x3f773eb8,0xbe893f6f,0x3f5fbecf,0x3efc3f6a,0xbf7fbe2f,0x3d97bf7c,0xbf423f13,0xbf27bf51,
0x3f7ebcc9,0x3dfb3f80,0x3f1dbf39,0x3f4a3f31,0xbf733e60,0xbea1bf7a,0xbee63f58,0xbf65bf09,0xbec43f6d,0xbf6dbec4,0xbec43f6d,0xbf6dbec4,
0x3ec4bf6d,0x3f6d3ec4,0x3ec4bf6d,0x3f6d3ec4,0xbec43f6d,0xbf6dbec4,0xbec43f6d,0xbf6dbec4,0x3ec4bf6d,0x3f6d3ec4,0x3ec4bf6d,0x3f6d3ec4,
0xbf5fbecf,0x3efcbf6a,0xbe89bf6f,0x3f77beb8,0x3f423f13,0xbf273f51,0x3d973f7c,0xbf7f3e2f,0xbf1dbf39,0x3f4abf31,0x3dfbbf80,0x3f7e3cc9,
0x3ee63f58,0xbf653f09,0xbea13f7a,0xbf73be60,0x3f18bf67,0x3f4e3edb,0x3f4e3edb,0xbf183f67,0xbf5c3f2c,0xbf04bf3e,0xbf04bf3e,0x3f5cbf2c,
0x3f7dbeac,0x3e163f71,0x3e163f71,0xbf7d3eac,0xbf78bd49,0x3e79bf80,0x3e79bf80,0x3f783d49,0x3f393ee6,0xbf313f65,0xbf803ea1,0xbcc9bf73,
0xbe60bf5f,0x3f7abefc,0x3f583e89,0xbf093f77,0xbeb83f7f,0xbf6fbd97,0xbecfbf42,0x3f6abf27,0x3f51bf4a,0x3f133f1d,0xbe2f3f7e,0xbf7c3dfb,
0xbf463f62,0xbf22bef1,0x3f46bf62,0x3f223ef1,0x3f7fbe95,0xbdc93f75,0xbf7f3e95,0x3dc9bf75,0xbf22bef1,0x3f46bf62,0x3f223ef1,0xbf463f62,
0xbdc93f75,0xbf7f3e95,0x3dc9bf75,0x3f7fbe95,0xbf09befc,0x3f58bf5f,0xbe603f77,0xbf7a3e89,0xbecf3f7f,0xbf6a3d97,0x3f6fbf42,0x3eb83f27,
0x3f7cbf1d,0x3e2f3f4a,0xbf51bdfb,0x3f13bf7e,0xbf31bea1,0x3f39bf73,0xbcc93f65,0xbf803ee6,0x3f67bf5c,0x3edb3f04,0xbedbbf04,0x3f67bf5c,
0xbf3ebe16,0x3f2cbf7d,0xbf2c3f7d,0xbf3ebe16,0xbeac3f78,0xbf713e79,0x3f71be79,0xbeac3f78,0x3f80bf18,0x3d493f4e,0xbd49bf4e,0x3f80bf18,
0x3ea13f09,0xbf733f58,0x3f65be60,0xbee63f7a,0x3f5fbf6f,0x3efc3eb8,0x3e89bf6a,0x3f77becf,0xbf27be2f,0x3f42bf7c,0xbf7f3f13,0x3d97bf51,
0xbf1d3f80,0xbf4a3cc9,0x3dfb3f31,0xbf7e3f39,0xbf7b3f55,0xbe48bf0e,0xbf7b3f55,0xbe48bf0e,0x3e483f0e,0xbf7b3f55,0x3e483f0e,0xbf7b3f55,
0x3f7bbf55,0x3e483f0e,0x3f7bbf55,0x3e483f0e,0xbe48bf0e,0x3f7bbf55,0xbe48bf0e,0x3f7bbf55,0xbd97bf13,0x3f7fbf51,0x3f27bf7c,0x3f42be2f,
0xbf7e3f31,0x3dfbbf39,0xbf1dbcc9,0x3f4abf80,0xbea13f58,0xbf733f09,0xbf653f7a,0xbee6be60,0x3f5fbeb8,0xbefc3f6f,0x3e893ecf,0xbf773f6a,
0x3f80bf4e,0xbd493f18,0xbd493f18,0xbf803f4e,0x3edbbf5c,0x3f67bf04,0x3f67bf04,0xbedb3f5c,0xbf2c3e16,0x3f3ebf7d,0x3f3ebf7d,0x3f2cbe16,
0xbf713f78,0xbeacbe79,0xbeacbe79,0x3f71bf78,0xbe2f3f1d,0xbf7c3f4a,0xbf133dfb,0x3f51bf7e,0x3f39bea1,0xbf313f73,0xbf803f65,0xbcc9bee6,
0x3f7abf77,0x3e603e89,0xbf093f5f,0xbf583efc,0x3eb8bf42,0x3f6fbf27,0x3ecf3d97,0xbf6a3f7f,0xbf753f46,0x3e95bf22,0x3f75bf46,0xbe953f22,
0xbf623f7f,0xbef13dc9,0x3f62bf7f,0x3ef1bdc9,0xbe953f22,0xbf753f46,0x3e95bf22,0x3f75bf46,0x3ef1bdc9,0xbf623f7f,0xbef13dc9,0x3f62bf7f,
0x3ecfbf27,0x3f6abf42,0xbf6f3f7f,0xbeb83d97,0xbe2fbdfb,0x3f7cbf7e,0xbf133f4a,0xbf513f1d,0xbf313ee6,0x3f39bf65,0xbcc93ea1,0xbf803f73,
0xbf7a3f5f,0x3e60befc,0x3f09be89,0xbf583f77,0x3f5cbf3e,0xbf043f2c,0x3f04bf2c,0x3f5cbf3e,0x3f7dbf71,0xbe163eac,0x3e16beac,0x3f7dbf71,
0x3f78bf80,0x3e79bd49,0xbe793d49,0x3f78bf80,0x3f4ebf67,0x3f18bedb,0xbf183edb,0x3f4ebf67,0xbf1d3f31,0xbf4a3f39,0x3dfbbcc9,0xbf7e3f80,
0xbee63f09,0xbf653f58,0x3ea1be60,0xbf733f7a,0xbe893eb8,0xbf773f6f,0x3efcbecf,0xbf5f3f6a,0xbd973e2f,0xbf7f3f7c,0x3f27bf13,0xbf423f51,
0x3f803f80,0xbf353f35,0x3f803f80,0xbf353f35,0x3f803f80,0xbf353f35,0x3f803f80,0xbf353f35,0x3f803f80,0xbf353f35,0x3f803f80,0xbf353f35,
0x3f803f80,0xbf353f35,0x3f803f80,0xbf353f35,0xbf7ebf80,0x3dfb3cc9,0xbf1dbf31,0x3f4a3f39,0xbf73bf7a,0x3ea13e60,0xbee6bf09,0x3f653f58,
0xbf5fbf6a,0x3efc3ecf,0xbe89beb8,0x3f773f6f,0xbf42bf51,0x3f273f13,0xbd97be2f,0x3f7f3f7c,0x3f783f80,0xbe79bd49,0xbe79bd49,0xbf78bf80,
0x3f4e3f67,0xbf18bedb,0xbf18bedb,0xbf4ebf67,0x3f043f2c,0xbf5cbf3e,0xbf5cbf3e,0xbf04bf2c,0x3e163eac,0xbf7dbf71,0xbf7dbf71,0xbe16beac,
0xbf6fbf7f,0x3eb83d97,0x3f6a3f42,0x3ecf3f27,0xbf13bf4a,0x3f513f1d,0x3f7c3f7e,0xbe2f3dfb,0xbcc9bea1,0x3f803f73,0x3f393f65,0xbf31bee6,
0x3f093e89,0x3f583f77,0x3e603efc,0xbf7abf5f,0x3f623f7f,0xbef1bdc9,0xbf62bf7f,0x3ef13dc9,0x3e953f22,0xbf75bf46,0xbe95bf22,0x3f753f46,
0xbef1bdc9,0xbf62bf7f,0x3ef13dc9,0x3f623f7f,0xbf75bf46,0xbe95bf22,0x3f753f46,0x3e953f22,0xbf51bf7e,0x3f133dfb,0x3e2f3f1d,0xbf7cbf4a,
0x3cc9bee6,0x3f803f65,0xbf39bea1,0xbf31bf73,0x3f583efc,0x3f093f5f,0xbf7abf77,0x3e60be89,0x3f6a3f7f,0xbecf3d97,0xbeb8bf42,0x3f6f3f27,
0x3f3e3f7d,0xbf2cbe16,0x3f2c3e16,0x3f3e3f7d,0xbeac3e79,0xbf71bf78,0x3f713f78,0xbeac3e79,0xbf80bf4e,0xbd49bf18,0x3d493f18,0xbf80bf4e,
0xbedbbf5c,0x3f673f04,0xbf67bf04,0xbedbbf5c,0xbf27bf7c,0x3f423e2f,0xbf7fbf51,0x3d97bf13,0x3f1dbcc9,0x3f4a3f80,0xbdfbbf39,0x3f7e3f31,
0x3f653f7a,0xbee63e60,0x3f733f09,0x3ea13f58,0xbe893ecf,0xbf77bf6a,0x3efc3f6f,0xbf5fbeb8,0x3f0e3f7b,0xbf55be48,0x3f0e3f7b,0xbf55be48,
0xbf55be48,0xbf0ebf7b,0xbf55be48,0xbf0ebf7b,0xbf0ebf7b,0x3f553e48,0xbf0ebf7b,0x3f553e48,0x3f553e48,0x3f0e3f7b,0x3f553e48,0x3f0e3f7b,
0xbee6bf7a,0x3f653e60,0x3ea1bf09,0x3f733f58,0x3f773ecf,0x3e893f6a,0x3f5f3f6f,0xbefc3eb8,0x3d973f51,0xbf7fbf13,0xbf273e2f,0xbf42bf7c,
0xbf7ebf39,0x3dfbbf31,0xbf1dbf80,0x3f4a3cc9,0x3eac3f78,0xbf71be79,0xbf71be79,0xbeacbf78,0xbf80bf18,0x3d49bf4e,0x3d49bf4e,0x3f803f18,
0x3edbbf04,0x3f673f5c,0x3f673f5c,0xbedb3f04,0x3f2c3f7d,0xbf3e3e16,0xbf3e3e16,0xbf2cbf7d,0xbe60bf77,0x3f7a3e89,0x3f583f5f,0xbf093efc,
0x3f6f3f42,0xbeb83f27,0xbf6abd97,0xbecfbf7f,0xbf513dfb,0xbf13bf7e,0x3e2fbf4a,0x3f7c3f1d,0xbcc9bf65,0x3f803ee6,0x3f393f73,0xbf313ea1,
0x3dc93f75,0xbf7fbe95,0xbdc9bf75,0x3f7f3e95,0xbf46bf62,0x3f22bef1,0x3f463f62,0xbf223ef1,0x3f7f3e95,0x3dc93f75,0xbf7fbe95,0xbdc9bf75,
0xbf223ef1,0xbf46bf62,0x3f22bef1,0x3f463f62,0x3cc9bf73,0x3f803ea1,0xbf393ee6,0xbf31bf65,0x3f093f77,0xbf583e89,0x3e60bf5f,0x3f7a3efc,
0xbf6abf27,0x3ecfbf42,0x3eb83f7f,0xbf6f3d97,0x3f7c3dfb,0x3e2f3f7e,0xbf51bf4a,0x3f13bf1d,0xbe163f71,0xbf7dbeac,0x3f7d3eac,0xbe163f71,
0xbe79bf80,0x3f78bd49,0xbf783d49,0xbe79bf80,0x3f183f67,0xbf4e3edb,0x3f4ebedb,0x3f183f67,0xbf5cbf2c,0x3f04bf3e,0xbf043f3e,0xbf5cbf2c,
0x3e89bf6f,0x3f773eb8,0xbefcbf6a,0x3f5fbecf,0xbd973f7c,0xbf7fbe2f,0x3f273f51,0xbf423f13,0xbdfbbf80,0x3f7ebcc9,0xbf4abf31,0x3f1dbf39,
0x3ea13f7a,0xbf733e60,0x3f653f09,0xbee63f58,0xbec43f6d,0xbf6dbec4,0xbec43f6d,0xbf6dbec4,0x3ec4bf6d,0x3f6d3ec4,0x3ec4bf6d,0x3f6d3ec4,
0xbec43f6d,0xbf6dbec4,0xbec43f6d,0xbf6dbec4,0x3ec4bf6d,0x3f6d3ec4,0x3ec4bf6d,0x3f6d3ec4,0x3efcbf6a,0x3f5f3ecf,0x3f77beb8,0x3e893f6f,
0xbf273f51,0xbf42bf13,0xbf7f3e2f,0xbd97bf7c,0x3f4abf31,0x3f1d3f39,0x3f7e3cc9,0xbdfb3f80,0xbf653f09,0xbee6bf58,0xbf73be60,0x3ea1bf7a,
0xbf183f67,0xbf4ebedb,0xbf4ebedb,0x3f18bf67,0x3f5cbf2c,0x3f043f3e,0x3f043f3e,0xbf5c3f2c,0xbf7d3eac,0xbe16bf71,0xbe16bf71,0x3f7dbeac,
0x3f783d49,0xbe793f80,0xbe793f80,0xbf78bd49,0x3f31bf65,0x3f393ee6,0x3cc93f73,0xbf803ea1,0xbf7a3efc,0xbe60bf5f,0x3f09bf77,0x3f583e89,
0x3f6f3d97,0xbeb83f7f,0xbf6a3f27,0xbecfbf42,0xbf13bf1d,0x3f51bf4a,0x3f7cbdfb,0xbe2f3f7e,0xbf463f62,0xbf22bef1,0x3f46bf62,0x3f223ef1,
0x3f7fbe95,0xbdc93f75,0xbf7f3e95,0x3dc9bf75,0xbf22bef1,0x3f46bf62,0x3f223ef1,0xbf463f62,0xbdc93f75,0xbf7f3e95,0x3dc9bf75,0x3f7fbe95,
0x3f58bf5f,0x3f093efc,0xbf7a3e89,0x3e60bf77,0xbf6a3d97,0x3ecfbf7f,0x3eb83f27,0xbf6f3f42,0x3e2f3f4a,0xbf7c3f1d,0x3f13bf7e,0x3f513dfb,
0x3f39bf73,0x3f313ea1,0xbf803ee6,0x3cc9bf65,0xbf673f5c,0xbedbbf04,0x3edb3f04,0xbf673f5c,0x3f3e3e16,0xbf2c3f7d,0x3f2cbf7d,0x3f3e3e16,
0x3eacbf78,0x3f71be79,0xbf713e79,0x3eacbf78,0xbf803f18,0xbd49bf4e,0x3d493f4e,0xbf803f18,0x3f73bf58,0x3ea13f09,0x3ee6bf7a,0x3f65be60,
0xbefcbeb8,0x3f5fbf6f,0xbf773ecf,0x3e89bf6a,0xbf423f7c,0xbf27be2f,0xbd973f51,0xbf7f3f13,0x3f4abcc9,0xbf1d3f80,0x3f7ebf39,0x3dfb3f31,
0xbf7b3f55,0xbe48bf0e,0xbf7b3f55,0xbe48bf0e,0x3e483f0e,0xbf7b3f55,0x3e483f0e,0xbf7b3f55,0x3f7bbf55,0x3e483f0e,0x3f7bbf55,0x3e483f0e,
0xbe48bf0e,0x3f7bbf55,0xbe48bf0e,0x3f7bbf55,0x3f7fbf51,0x3d973f13,0x3f42be2f,0xbf273f7c,0x3dfbbf39,0x3f7ebf31,0x3f4abf80,0x3f1d3cc9,
0xbf733f09,0x3ea1bf58,0xbee6be60,0x3f65bf7a,0xbefc3f6f,0xbf5f3eb8,0xbf773f6a,0xbe89becf,0xbf803f4e,0x3d49bf18,0x3d49bf18,0x3f80bf4e,
0xbedb3f5c,0xbf673f04,0xbf673f04,0x3edbbf5c,0x3f2cbe16,0xbf3e3f7d,0xbf3e3f7d,0xbf2c3e16,0x3f71bf78,0x3eac3e79,0x3eac3e79,0xbf713f78,
0x3f7cbf4a,0xbe2f3f1d,0xbf513f7e,0xbf133dfb,0x3f31bf73,0x3f39bea1,0x3cc93ee6,0xbf803f65,0xbe60be89,0x3f7abf77,0x3f58befc,0xbf093f5f,
0xbf6f3f27,0x3eb8bf42,0x3f6abf7f,0x3ecf3d97,0xbf753f46,0x3e95bf22,0x3f75bf46,0xbe953f22,0xbf623f7f,0xbef13dc9,0x3f62bf7f,0x3ef1bdc9,
0xbe953f22,0xbf753f46,0x3e95bf22,0x3f75bf46,0x3ef1bdc9,0xbf623f7f,0xbef13dc9,0x3f62bf7f,0x3f6abf42,0xbecf3f27,0xbeb83d97,0x3f6fbf7f,
0x3f7cbf7e,0x3e2f3dfb,0xbf513f1d,0x3f13bf4a,0x3f39bf65,0x3f31bee6,0xbf803f73,0x3cc9bea1,0x3e60befc,0x3f7abf5f,0xbf583f77,0xbf093e89,
0xbf5c3f3e,0x3f04bf2c,0xbf043f2c,0xbf5c3f3e,0xbf7d3f71,0x3e16beac,0xbe163eac,0xbf7d3f71,0xbf783f80,0xbe793d49,0x3e79bd49,0xbf783f80,
0xbf4e3f67,0xbf183edb,0x3f18bedb,0xbf4e3f67,0x3f4abf39,0xbf1d3f31,0x3f7ebf80,0x3dfbbcc9,0x3f65bf58,0xbee63f09,0x3f73bf7a,0x3ea1be60,
0x3f77bf6f,0xbe893eb8,0x3f5fbf6a,0x3efcbecf,0x3f7fbf7c,0xbd973e2f,0x3f42bf51,0x3f27bf13,0x3f803f80,0xbf353f35,0x3f803f80,0xbf353f35,
0x3f803f80,0xbf353f35,0x3f803f80,0xbf353f35,0x3f803f80,0xbf353f35,0x3f803f80,0xbf353f35,0x3f803f80,0xbf353f35,0x3f803f80,0xbf353f35,
0x3dfb3cc9,0x3f7e3f80,0x3f4a3f39,0x3f1d3f31,0x3ea13e60,0x3f733f7a,0x3f653f58,0x3ee63f09,0x3efc3ecf,0x3f5f3f6a,0x3f773f6f,0x3e893eb8,
0x3f273f13,0x3f423f51,0x3f7f3f7c,0x3d973e2f,0xbf78bf80,0x3e793d49,0x3e793d49,0x3f783f80,0xbf4ebf67,0x3f183edb,0x3f183edb,0x3f4e3f67,
0xbf04bf2c,0x3f5c3f3e,0x3f5c3f3e,0x3f043f2c,0xbe16beac,0x3f7d3f71,0x3f7d3f71,0x3e163eac,0xbeb8bd97,0xbf6fbf7f,0xbecfbf27,0x3f6a3f42,
0xbf51bf1d,0xbf13bf4a,0x3e2fbdfb,0x3f7c3f7e,0xbf80bf73,0xbcc9bea1,0x3f313ee6,0x3f393f65,0xbf58bf77,0x3f093e89,0x3f7a3f5f,0x3e603efc,
0x3f623f7f,0xbef1bdc9,0xbf62bf7f,0x3ef13dc9,0x3e953f22,0xbf75bf46,0xbe95bf22,0x3f753f46,0xbef1bdc9,0xbf62bf7f,0x3ef13dc9,0x3f623f7f,
0xbf75bf46,0xbe95bf22,0x3f753f46,0x3e953f22,0x3f133dfb,0x3f513f7e,0xbf7cbf4a,0xbe2fbf1d,0x3f803f65,0xbcc93ee6,0xbf31bf73,0x3f393ea1,
0x3f093f5f,0xbf58befc,0x3e60be89,0x3f7a3f77,0xbecf3d97,0xbf6abf7f,0x3f6f3f27,0x3eb83f42,0xbf3ebf7d,0x3f2c3e16,0xbf2cbe16,0xbf3ebf7d,
0x3eacbe79,0x3f713f78,0xbf71bf78,0x3eacbe79,0x3f803f4e,0x3d493f18,0xbd49bf18,0x3f803f4e,0x3edb3f5c,0xbf67bf04,0x3f673f04,0x3edb3f5c,
0xbf42be2f,0xbf27bf7c,0xbd973f13,0xbf7fbf51,0xbf4abf80,0x3f1dbcc9,0xbf7ebf31,0xbdfbbf39,0x3ee6be60,0x3f653f7a,0xbea1bf58,0x3f733f09,
0x3f773f6a,0xbe893ecf,0x3f5f3eb8,0x3efc3f6f,0x3f0e3f7b,0xbf55be48,0x3f0e3f7b,0xbf55be48,0xbf55be48,0xbf0ebf7b,0xbf55be48,0xbf0ebf7b,
0xbf0ebf7b,0x3f553e48,0xbf0ebf7b,0x3f553e48,0x3f553e48,0x3f0e3f7b,0x3f553e48,0x3f0e3f7b,0x3f653e60,0x3ee63f7a,0x3f733f58,0xbea13f09,
0x3e893f6a,0xbf77becf,0xbefc3eb8,0xbf5fbf6f,0xbf7fbf13,0xbd97bf51,0xbf42bf7c,0x3f27be2f,0x3dfbbf31,0x3f7e3f39,0x3f4a3cc9,0x3f1d3f80,
0xbeacbf78,0x3f713e79,0x3f713e79,0x3eac3f78,0x3f803f18,0xbd493f4e,0xbd493f4e,0xbf80bf18,0xbedb3f04,0xbf67bf5c,0xbf67bf5c,0x3edbbf04,
0xbf2cbf7d,0x3f3ebe16,0x3f3ebe16,0x3f2c3f7d,0xbf7abe89,0xbe60bf77,0x3f09befc,0x3f583f5f,0x3eb8bf27,0x3f6f3f42,0x3ecf3f7f,0xbf6abd97,
0x3f133f7e,0xbf513dfb,0xbf7cbf1d,0x3e2fbf4a,0xbf80bee6,0xbcc9bf65,0x3f31bea1,0x3f393f73,0x3dc93f75,0xbf7fbe95,0xbdc9bf75,0x3f7f3e95,
0xbf46bf62,0x3f22bef1,0x3f463f62,0xbf223ef1,0x3f7f3e95,0x3dc93f75,0xbf7fbe95,0xbdc9bf75,0xbf223ef1,0xbf46bf62,0x3f22bef1,0x3f463f62,
0x3f803ea1,0xbcc93f73,0xbf31bf65,0x3f39bee6,0xbf583e89,0xbf09bf77,0x3f7a3efc,0xbe603f5f,0x3ecfbf42,0x3f6a3f27,0xbf6f3d97,0xbeb8bf7f,
0x3e2f3f7e,0xbf7cbdfb,0x3f13bf1d,0x3f513f4a,0x3e16bf71,0x3f7d3eac,0xbf7dbeac,0x3e16bf71,0x3e793f80,0xbf783d49,0x3f78bd49,0x3e793f80,
0xbf18bf67,0x3f4ebedb,0xbf4e3edb,0xbf18bf67,0x3f5c3f2c,0xbf043f3e,0x3f04bf3e,0x3f5c3f2c,0xbf77beb8,0x3e89bf6f,0xbf5f3ecf,0xbefcbf6a,
0x3f7f3e2f,0xbd973f7c,0x3f42bf13,0x3f273f51,0xbf7e3cc9,0xbdfbbf80,0xbf1d3f39,0xbf4abf31,0x3f73be60,0x3ea13f7a,0x3ee6bf58,0x3f653f09,
0xbec43f6d,0xbf6dbec4,0xbec43f6d,0xbf6dbec4,0x3ec4bf6d,0x3f6d3ec4,0x3ec4bf6d,0x3f6d3ec4,0xbec43f6d,0xbf6dbec4,0xbec43f6d,0xbf6dbec4,
0x3ec4bf6d,0x3f6d3ec4,0x3ec4bf6d,0x3f6d3ec4,0x3f5f3ecf,0xbefc3f6a,0x3e893f6f,0xbf773eb8,0xbf42bf13,0x3f27bf51,0xbd97bf7c,0x3f7fbe2f,
0x3f1d3f39,0xbf4a3f31,0xbdfb3f80,0xbf7ebcc9,0xbee6bf58,0x3f65bf09,0x3ea1bf7a,0x3f733e60,0x3f18bf67,0x3f4e3edb,0x3f4e3edb,0xbf183f67,
0xbf5c3f2c,0xbf04bf3e,0xbf04bf3e,0x3f5cbf2c,0x3f7dbeac,0x3e163f71,0x3e163f71,0xbf7d3eac,0xbf78bd49,0x3e79bf80,0x3e79bf80,0x3f783d49,
0xbf39bee6,0x3f31bf65,0x3f80bea1,0x3cc93f73,0x3e603f5f,0xbf7a3efc,0xbf58be89,0x3f09bf77,0x3eb8bf7f,0x3f6f3d97,0x3ecf3f42,0xbf6a3f27,
0xbf513f4a,0xbf13bf1d,0x3e2fbf7e,0x3f7cbdfb,0xbf463f62,0xbf22bef1,0x3f46bf62,0x3f223ef1,0x3f7fbe95,0xbdc93f75,0xbf7f3e95,0x3dc9bf75,
0xbf22bef1,0x3f46bf62,0x3f223ef1,0xbf463f62,0xbdc93f75,0xbf7f3e95,0x3dc9bf75,0x3f7fbe95,0x3f093efc,0xbf583f5f,0x3e60bf77,0x3f7abe89,
0x3ecfbf7f,0x3f6abd97,0xbf6f3f42,0xbeb8bf27,0xbf7c3f1d,0xbe2fbf4a,0x3f513dfb,0xbf133f7e,0x3f313ea1,0xbf393f73,0x3cc9bf65,0x3f80bee6,
0x3f67bf5c,0x3edb3f04,0xbedbbf04,0x3f67bf5c,0xbf3ebe16,0x3f2cbf7d,0xbf2c3f7d,0xbf3ebe16,0xbeac3f78,0xbf713e79,0x3f71be79,0xbeac3f78,
0x3f80bf18,0x3d493f4e,0xbd49bf4e,0x3f80bf18,0xbea1bf09,0x3f73bf58,0xbf653e60,0x3ee6bf7a,0xbf5f3f6f,0xbefcbeb8,0xbe893f6a,0xbf773ecf,
0x3f273e2f,0xbf423f7c,0x3f7fbf13,0xbd973f51,0x3f1dbf80,0x3f4abcc9,0xbdfbbf31,0x3f7ebf39,0xbf7b3f55,0xbe48bf0e,0xbf7b3f55,0xbe48bf0e,
0x3e483f0e,0xbf7b3f55,0x3e483f0e,0xbf7b3f55,0x3f7bbf55,0x3e483f0e,0x3f7bbf55,0x3e483f0e,0xbe48bf0e,0x3f7bbf55,0xbe48bf0e,0x3f7bbf55,
0x3d973f13,0xbf7f3f51,0xbf273f7c,0xbf423e2f,0x3f7ebf31,0xbdfb3f39,0x3f1d3cc9,0xbf4a3f80,0x3ea1bf58,0x3f73bf09,0x3f65bf7a,0x3ee63e60,
0xbf5f3eb8,0x3efcbf6f,0xbe89becf,0x3f77bf6a,0x3f80bf4e,0xbd493f18,0xbd493f18,0xbf803f4e,0x3edbbf5c,0x3f67bf04,0x3f67bf04,0xbedb3f5c,
0xbf2c3e16,0x3f3ebf7d,0x3f3ebf7d,0x3f2cbe16,0xbf713f78,0xbeacbe79,0xbeacbe79,0x3f71bf78,0x3e2fbf1d,0x3f7cbf4a,0x3f13bdfb,0xbf513f7e,
0xbf393ea1,0x3f31bf73,0x3f80bf65,0x3cc93ee6,0xbf7a3f77,0xbe60be89,0x3f09bf5f,0x3f58befc,0xbeb83f42,0xbf6f3f27,0xbecfbd97,0x3f6abf7f,
0xbf753f46,0x3e95bf22,0x3f75bf46,0xbe953f22,0xbf623f7f,0xbef13dc9,0x3f62bf7f,0x3ef1bdc9,0xbe953f22,0xbf753f46,0x3e95bf22,0x3f75bf46,
0x3ef1bdc9,0xbf623f7f,0xbef13dc9,0x3f62bf7f,0xbecf3f27,0xbf6a3f42,0x3f6fbf7f,0x3eb8bd97,0x3e2f3dfb,0xbf7c3f7e,0x3f13bf4a,0x3f51bf1d,
0x3f31bee6,0xbf393f65,0x3cc9bea1,0x3f80bf73,0x3f7abf5f,0xbe603efc,0xbf093e89,0x3f58bf77,0x3f5cbf3e,0xbf043f2c,0x3f04bf2c,0x3f5cbf3e,
0x3f7dbf71,0xbe163eac,0x3e16beac,0x3f7dbf71,0x3f78bf80,0x3e79bd49,0xbe793d49,0x3f78bf80,0x3f4ebf67,0x3f18bedb,0xbf183edb,0x3f4ebf67,
0x3f1dbf31,0x3f4abf39,0xbdfb3cc9,0x3f7ebf80,0x3ee6bf09,0x3f65bf58,0xbea13e60,0x3f73bf7a,0x3e89beb8,0x3f77bf6f,0xbefc3ecf,0x3f5fbf6a,
0x3d97be2f,0x3f7fbf7c,0xbf273f13,0x3f42bf51,0x3f803f80,0xbf803f80,0x3f803f80,0xbf803f80,0x3f803f80,0xbf803f80,0x3f803f80,0xbf803f80,
0x3f803f80,0xbf803f80,0x3f803f80,0xbf803f80,0x3f803f80,0xbf803f80,0x3f803f80,0xbf803f80,0x3f7d3f80,0xbe16bd49,0x3f183f2c,0xbf4ebf3e,
0x3f713f78,0xbeacbe79,0x3edb3f04,0xbf67bf5c,0x3f5c3f67,0xbf04bedb,0x3e793eac,0xbf78bf71,0x3f3e3f4e,0xbf2cbf18,0x3d493e16,0xbf80bf7d,
0x3f753f7f,0xbe95bdc9,0xbe95bdc9,0xbf75bf7f,0x3f463f62,0xbf22bef1,0xbf22bef1,0xbf46bf62,0x3ef13f22,0xbf62bf46,0xbf62bf46,0xbef1bf22,
0x3dc93e95,0xbf7fbf75,0xbf7fbf75,0xbdc9be95,0x3f673f7d,0xbedbbe16,0xbf71bf4e,0xbeacbf18,0x3f043f3e,0xbf5cbf2c,0xbf78bf80,0x3e79bd49,
0xbd493e79,0xbf80bf78,0xbf2cbf5c,0x3f3e3f04,0xbf18beac,0xbf4ebf71,0xbe16bedb,0x3f7d3f67,0x3f553f7b,0xbf0ebe48,0xbf55bf7b,0x3f0e3e48,
0x3e483f0e,0xbf7bbf55,0xbe48bf0e,0x3f7b3f55,0xbf0ebe48,0xbf55bf7b,0x3f0e3e48,0x3f553f7b,0xbf7bbf55,0xbe48bf0e,0x3f7b3f55,0x3e483f0e,
0x3f3e3f78,0xbf2cbe79,0xbd49bf04,0x3f803f5c,0xbe163eac,0xbf7dbf71,0x3f4e3edb,0x3f183f67,0xbf67bf18,0xbedbbf4e,0x3f713f7d,0xbeac3e16,
0xbf5cbf80,0x3f043d49,0x3e793f2c,0xbf78bf3e,0x3f223f75,0xbf46be95,0x3f463e95,0x3f223f75,0xbef13dc9,0xbf62bf7f,0x3f623f7f,0xbef13dc9,
0xbf7fbf62,0x3dc9bef1,0xbdc93ef1,0xbf7fbf62,0xbe95bf46,0x3f753f22,0xbf75bf22,0xbe95bf46,0x3f043f71,0xbf5cbeac,0x3f783f67,0xbe793edb,
0xbf3ebe16,0xbf2cbf7d,0xbd493f18,0xbf80bf4e,0xbf4ebf80,0x3f18bd49,0xbf7dbf2c,0xbe16bf3e,0x3edbbe79,0x3f673f78,0xbeacbf5c,0x3f713f04,
0x3ec43f6d,0xbf6dbec4,0x3ec43f6d,0xbf6dbec4,0xbf6dbec4,0xbec4bf6d,0xbf6dbec4,0xbec4bf6d,0xbec4bf6d,0x3f6d3ec4,0xbec4bf6d,0x3f6d3ec4,
0x3f6d3ec4,0x3ec43f6d,0x3f6d3ec4,0x3ec43f6d,0x3e793f67,0xbf78bedb,0xbf043eac,0xbf5cbf71,0xbf80bf18,0xbd49bf4e,0xbf3ebf7d,0x3f2cbe16,
0x3e16bf2c,0x3f7d3f3e,0x3f4e3d49,0x3f183f80,0x3f713f5c,0xbeac3f04,0x3edb3f78,0xbf67be79,0x3dc93f62,0xbf7fbef1,0xbf7fbef1,0xbdc9bf62,
0xbf75bf46,0x3e95bf22,0x3e95bf22,0x3f753f46,0x3f22be95,0x3f463f75,0x3f463f75,0xbf223e95,0x3ef13f7f,0xbf62bdc9,0xbf62bdc9,0xbef1bf7f,
0xbd493f5c,0xbf80bf04,0xbf2cbf78,0x3f3ebe79,0xbf4ebf67,0x3f18bedb,0x3f7d3eac,0x3e163f71,0x3f713e16,0x3eac3f7d,0xbedb3f18,0xbf67bf4e,
0xbe793f3e,0xbf78bf2c,0xbf04bf80,0x3f5cbd49,0xbe483f55,0xbf7bbf0e,0x3e48bf55,0x3f7b3f0e,0xbf0ebf7b,0x3f55be48,0x3f0e3f7b,0xbf553e48,
0x3f7b3f0e,0xbe483f55,0xbf7bbf0e,0x3e48bf55,0xbf553e48,0xbf0ebf7b,0x3f55be48,0x3f0e3f7b,0xbeac3f4e,0xbf71bf18,0x3f67be16,0x3edb3f7d,
0xbe79bf80,0x3f783d49,0xbf043f2c,0xbf5cbf3e,0x3f3e3f5c,0xbf2c3f04,0xbd49bf78,0x3f803e79,0xbf7dbedb,0x3e16bf67,0x3f183f71,0xbf4e3eac,
0xbef13f46,0xbf62bf22,0x3f623f22,0xbef13f46,0x3dc9bf75,0x3f7f3e95,0xbf7fbe95,0x3dc9bf75,0x3e953f7f,0xbf753dc9,0x3f75bdc9,0x3e953f7f,
0xbf22bf62,0x3f46bef1,0xbf463ef1,0xbf22bf62,0xbf183f3e,0xbf4ebf2c,0x3e163f80,0xbf7d3d49,0x3edbbf5c,0x3f673f04,0xbeacbf78,0x3f71be79,
0xbe793f71,0xbf78beac,0x3f043f67,0xbf5c3edb,0x3d49bf7d,0x3f803e16,0xbf2cbf4e,0x3f3ebf18,0xbf353f35,0xbf35bf35,0xbf353f35,0xbf35bf35,
0x3f35bf35,0x3f353f35,0x3f35bf35,0x3f353f35,0xbf353f35,0xbf35bf35,0xbf353f35,0xbf35bf35,0x3f35bf35,0x3f353f35,0x3f35bf35,0x3f353f35,
0xbf4e3f2c,0xbf18bf3e,0xbf7dbd49,0x3e16bf80,0x3f67bf04,0x3edb3f5c,0x3f713e79,0xbeac3f78,0xbf783eac,0xbe79bf71,0xbf5cbedb,0x3f04bf67,
0x3f80be16,0x3d493f7d,0x3f3e3f18,0xbf2c3f4e,0xbf623f22,0xbef1bf46,0xbef1bf46,0x3f62bf22,0x3f7fbe95,0x3dc93f75,0x3dc93f75,0xbf7f3e95,
0xbf75bdc9,0x3e95bf7f,0x3e95bf7f,0x3f753dc9,0x3f463ef1,0xbf223f62,0xbf223f62,0xbf46bef1,0xbf713f18,0xbeacbf4e,0x3edbbf7d,0x3f673e16,
0x3f78bd49,0xbe793f80,0xbf5c3f3e,0xbf04bf2c,0xbf2cbf04,0x3f3ebf5c,0x3f80be79,0xbd493f78,0x3e163f67,0xbf7d3edb,0xbf4ebeac,0x3f18bf71,
0xbf7b3f0e,0xbe48bf55,0x3f7bbf0e,0x3e483f55,0x3f553e48,0xbf0e3f7b,0xbf55be48,0x3f0ebf7b,0xbe48bf55,0x3f7bbf0e,0x3e483f55,0xbf7b3f0e,
0xbf0e3f7b,0xbf55be48,0x3f0ebf7b,0x3f553e48,0xbf803f04,0xbd49bf5c,0x3f3e3e79,0xbf2c3f78,0x3f183edb,0xbf4e3f67,0x3e16bf71,0x3f7dbeac,
0x3eacbf7d,0x3f71be16,0xbf673f4e,0xbedbbf18,0xbf783f2c,0xbe79bf3e,0x3f5c3d49,0xbf043f80,0xbf7f3ef1,0x3dc9bf62,0xbdc93f62,0xbf7f3ef1,
0x3e953f22,0xbf753f46,0x3f75bf46,0x3e953f22,0x3f46bf75,0x3f223e95,0xbf22be95,0x3f46bf75,0xbf623dc9,0x3ef1bf7f,0xbef13f7f,0xbf623dc9,
0xbf783edb,0x3e79bf67,0xbf5c3f71,0xbf04beac,0xbd493f4e,0xbf803f18,0x3f2c3e16,0xbf3e3f7d,0x3f7dbf3e,0x3e163f2c,0x3f18bf80,0x3f4ebd49,
0xbeacbf04,0x3f71bf5c,0xbf673e79,0x3edbbf78,0xbf6d3ec4,0x3ec4bf6d,0xbf6d3ec4,0x3ec4bf6d,0xbec43f6d,0xbf6d3ec4,0xbec43f6d,0xbf6d3ec4,
0x3f6dbec4,0xbec43f6d,0x3f6dbec4,0xbec43f6d,0x3ec4bf6d,0x3f6dbec4,0x3ec4bf6d,0x3f6dbec4,0xbf5c3eac,0x3f04bf71,0xbe79bedb,0x3f78bf67,
0xbf2c3f7d,0xbf3e3e16,0xbf803f4e,0xbd49bf18,0x3f183d49,0xbf4e3f80,0xbe163f3e,0xbf7d3f2c,0x3f67bf78,0x3edb3e79,0x3f71bf04,0xbeac3f5c,
0xbf463e95,0x3f22bf75,0x3f22bf75,0x3f46be95,0xbf623f7f,0xbef1bdc9,0xbef1bdc9,0x3f62bf7f,0x3dc93ef1,0xbf7f3f62,0xbf7f3f62,0xbdc9bef1,
0x3f75bf22,0xbe953f46,0xbe953f46,0xbf753f22,0xbf2c3e79,0x3f3ebf78,0x3f80bf5c,0xbd493f04,0xbf7d3f71,0xbe16beac,0x3f18bf67,0x3f4ebedb,
0xbedb3f4e,0xbf673f18,0xbeacbe16,0x3f71bf7d,0x3f04bd49,0xbf5c3f80,0xbf783f3e,0x3e79bf2c,0xbf0e3e48,0x3f55bf7b,0x3f0ebe48,0xbf553f7b,
0xbf7b3f55,0x3e48bf0e,0x3f7bbf55,0xbe483f0e,0xbf553f7b,0xbf0e3e48,0x3f55bf7b,0x3f0ebe48,0xbe483f0e,0xbf7b3f55,0x3e48bf0e,0x3f7bbf55,
0xbedb3e16,0x3f67bf7d,0xbeac3f18,0xbf713f4e,0xbf5c3f2c,0x3f04bf3e,0x3e793d49,0xbf783f80,0xbf803f78,0xbd49be79,0x3f3ebf04,0xbf2c3f5c,
0xbf4e3f71,0xbf183eac,0x3f7dbf67,0xbe163edb,0xbe953dc9,0x3f75bf7f,0xbf753f7f,0xbe953dc9,0xbf223ef1,0x3f46bf62,0xbf463f62,0xbf223ef1,
0xbf623f46,0x3ef1bf22,0xbef13f22,0xbf623f46,0xbf7f3f75,0x3dc9be95,0xbdc93e95,0xbf7f3f75,0xbe163d49,0x3f7dbf80,0xbf4e3f3e,0x3f18bf2c,
0xbeac3e79,0x3f71bf78,0xbf673f5c,0x3edbbf04,0xbf043edb,0x3f5cbf67,0xbf783f71,0x3e79beac,0xbf2c3f18,0x3f3ebf4e,0xbf803f7d,0x3d49be16,
0x3f803f80,0xbf803f80,0x3f803f80,0xbf803f80,0x3f803f80,0xbf803f80,0x3f803f80,0xbf803f80,0x3f803f80,0xbf803f80,0x3f803f80,0xbf803f80,
0x3f803f80,0xbf803f80,0x3f803f80,0xbf803f80,0xbe16bd49,0xbf7dbf80,0xbf4ebf3e,0xbf18bf2c,0xbeacbe79,0xbf71bf78,0xbf67bf5c,0xbedbbf04,
0xbf04bedb,0xbf5cbf67,0xbf78bf71,0xbe79beac,0xbf2cbf18,0xbf3ebf4e,0xbf80bf7d,0xbd49be16,0xbf75bf7f,0x3e953dc9,0x3e953dc9,0x3f753f7f,
0xbf46bf62,0x3f223ef1,0x3f223ef1,0x3f463f62,0xbef1bf22,0x3f623f46,0x3f623f46,0x3ef13f22,0xbdc9be95,0x3f7f3f75,0x3f7f3f75,0x3dc93e95,
0x3edb3e16,0x3f673f7d,0x3eac3f18,0xbf71bf4e,0x3f5c3f2c,0x3f043f3e,0xbe793d49,0xbf78bf80,0x3f803f78,0xbd493e79,0xbf3ebf04,0xbf2cbf5c,
0x3f4e3f71,0xbf18beac,0xbf7dbf67,0xbe16bedb,0x3f553f7b,0xbf0ebe48,0xbf55bf7b,0x3f0e3e48,0x3e483f0e,0xbf7bbf55,0xbe48bf0e,0x3f7b3f55,
0xbf0ebe48,0xbf55bf7b,0x3f0e3e48,0x3f553f7b,0xbf7bbf55,0xbe48bf0e,0x3f7b3f55,0x3e483f0e,0xbf2cbe79,0xbf3ebf78,0x3f803f5c,0x3d493f04,
0xbf7dbf71,0x3e16beac,0x3f183f67,0xbf4ebedb,0xbedbbf4e,0x3f673f18,0xbeac3e16,0xbf71bf7d,0x3f043d49,0x3f5c3f80,0xbf78bf3e,0xbe79bf2c,
0xbf22bf75,0x3f463e95,0xbf46be95,0xbf22bf75,0x3ef1bdc9,0x3f623f7f,0xbf62bf7f,0x3ef1bdc9,0x3f7f3f62,0xbdc93ef1,0x3dc9bef1,0x3f7f3f62,
0x3e953f46,0xbf75bf22,0x3f753f22,0x3e953f46,0x3f5c3eac,0x3f043f71,0x3e79bedb,0x3f783f67,0x3f2c3f7d,0xbf3ebe16,0x3f803f4e,0xbd493f18,
0xbf183d49,0xbf4ebf80,0x3e163f3e,0xbf7dbf2c,0xbf67bf78,0x3edbbe79,0xbf71bf04,0xbeacbf5c,0x3ec43f6d,0xbf6dbec4,0x3ec43f6d,0xbf6dbec4,
0xbf6dbec4,0xbec4bf6d,0xbf6dbec4,0xbec4bf6d,0xbec4bf6d,0x3f6d3ec4,0xbec4bf6d,0x3f6d3ec4,0x3f6d3ec4,0x3ec43f6d,0x3f6d3ec4,0x3ec43f6d,
0xbf78bedb,0xbe79bf67,0xbf5cbf71,0x3f04beac,0xbd49bf4e,0x3f803f18,0x3f2cbe16,0x3f3e3f7d,0x3f7d3f3e,0xbe163f2c,0x3f183f80,0xbf4ebd49,
0xbeac3f04,0xbf71bf5c,0xbf67be79,0xbedbbf78,0xbdc9bf62,0x3f7f3ef1,0x3f7f3ef1,0x3dc93f62,0x3f753f46,0xbe953f22,0xbe953f22,0xbf75bf46,
0xbf223e95,0xbf46bf75,0xbf46bf75,0x3f22be95,0xbef1bf7f,0x3f623dc9,0x3f623dc9,0x3ef13f7f,0x3f803f04,0xbd493f5c,0xbf3e3e79,0xbf2cbf78,
0xbf183edb,0xbf4ebf67,0xbe16bf71,0x3f7d3eac,0xbeacbf7d,0x3f713e16,0x3f673f4e,0xbedb3f18,0x3f783f2c,0xbe793f3e,0xbf5c3d49,0xbf04bf80,
0xbe483f55,0xbf7bbf0e,0x3e48bf55,0x3f7b3f0e,0xbf0ebf7b,0x3f55be48,0x3f0e3f7b,0xbf553e48,0x3f7b3f0e,0xbe483f55,0xbf7bbf0e,0x3e48bf55,
0xbf553e48,0xbf0ebf7b,0x3f55be48,0x3f0e3f7b,0xbf71bf18,0x3eacbf4e,0x3edb3f7d,0xbf673e16,0x3f783d49,0x3e793f80,0xbf5cbf3e,0x3f04bf2c,
0xbf2c3f04,0xbf3ebf5c,0x3f803e79,0x3d493f78,0x3e16bf67,0x3f7d3edb,0xbf4e3eac,0xbf18bf71,0x3ef1bf46,0x3f623f22,0xbf62bf22,0x3ef1bf46,
0xbdc93f75,0xbf7fbe95,0x3f7f3e95,0xbdc93f75,0xbe95bf7f,0x3f75bdc9,0xbf753dc9,0xbe95bf7f,0x3f223f62,0xbf463ef1,0x3f46bef1,0x3f223f62,
0x3f4e3f2c,0xbf183f3e,0x3f7dbd49,0x3e163f80,0xbf67bf04,0x3edbbf5c,0xbf713e79,0xbeacbf78,0x3f783eac,0xbe793f71,0x3f5cbedb,0x3f043f67,
0xbf80be16,0x3d49bf7d,0xbf3e3f18,0xbf2cbf4e,0xbf353f35,0xbf35bf35,0xbf353f35,0xbf35bf35,0x3f35bf35,0x3f353f35,0x3f35bf35,0x3f353f35,
0xbf353f35,0xbf35bf35,0xbf353f35,0xbf35bf35,0x3f35bf35,0x3f353f35,0x3f35bf35,0x3f353f35,0xbf18bf3e,0x3f4ebf2c,0x3e16bf80,0x3f7d3d49,
0x3edb3f5c,0xbf673f04,0xbeac3f78,0xbf71be79,0xbe79bf71,0x3f78beac,0x3f04bf67,0x3f5c3edb,0x3d493f7d,0xbf803e16,0xbf2c3f4e,0xbf3ebf18,
0x3f62bf22,0x3ef13f46,0x3ef13f46,0xbf623f22,0xbf7f3e95,0xbdc9bf75,0xbdc9bf75,0x3f7fbe95,0x3f753dc9,0xbe953f7f,0xbe953f7f,0xbf75bdc9,
0xbf46bef1,0x3f22bf62,0x3f22bf62,0x3f463ef1,0x3eac3f4e,0xbf713f18,0xbf67be16,0x3edbbf7d,0x3e79bf80,0x3f78bd49,0x3f043f2c,0xbf5c3f3e,
0xbf3e3f5c,0xbf2cbf04,0x3d49bf78,0x3f80be79,0x3f7dbedb,0x3e163f67,0xbf183f71,0xbf4ebeac,0xbf7b3f0e,0xbe48bf55,0x3f7bbf0e,0x3e483f55,
0x3f553e48,0xbf0e3f7b,0xbf55be48,0x3f0ebf7b,0xbe48bf55,0x3f7bbf0e,0x3e483f55,0xbf7b3f0e,0xbf0e3f7b,0xbf55be48,0x3f0ebf7b,0x3f553e48,
0xbd49bf5c,0x3f80bf04,0xbf2c3f78,0xbf3ebe79,0xbf4e3f67,0xbf18bedb,0x3f7dbeac,0xbe163f71,0x3f71be16,0xbeac3f7d,0xbedbbf18,0x3f67bf4e,
0xbe79bf3e,0x3f78bf2c,0xbf043f80,0xbf5cbd49,0x3f7fbef1,0xbdc93f62,0x3dc9bf62,0x3f7fbef1,0xbe95bf22,0x3f75bf46,0xbf753f46,0xbe95bf22,
0xbf463f75,0xbf22be95,0x3f223e95,0xbf463f75,0x3f62bdc9,0xbef13f7f,0x3ef1bf7f,0x3f62bdc9,0xbe793f67,0xbf783edb,0x3f043eac,0xbf5c3f71,
0x3f80bf18,0xbd493f4e,0x3f3ebf7d,0x3f2c3e16,0xbe16bf2c,0x3f7dbf3e,0xbf4e3d49,0x3f18bf80,0xbf713f5c,0xbeacbf04,0xbedb3f78,0xbf673e79,
0xbf6d3ec4,0x3ec4bf6d,0xbf6d3ec4,0x3ec4bf6d,0xbec43f6d,0xbf6d3ec4,0xbec43f6d,0xbf6d3ec4,0x3f6dbec4,0xbec43f6d,0x3f6dbec4,0xbec43f6d,
0x3ec4bf6d,0x3f6dbec4,0x3ec4bf6d,0x3f6dbec4,0x3f04bf71,0x3f5cbeac,0x3f78bf67,0x3e793edb,0xbf3e3e16,0x3f2cbf7d,0xbd49bf18,0x3f80bf4e,
0xbf4e3f80,0xbf18bd49,0xbf7d3f2c,0x3e16bf3e,0x3edb3e79,0xbf673f78,0xbeac3f5c,0xbf713f04,0x3f46be95,0xbf223f75,0xbf223f75,0xbf463e95,
0x3f62bf7f,0x3ef13dc9,0x3ef13dc9,0xbf623f7f,0xbdc9bef1,0x3f7fbf62,0x3f7fbf62,0x3dc93ef1,0xbf753f22,0x3e95bf46,0x3e95bf46,0x3f75bf22,
0xbf3e3f78,0xbf2c3e79,0x3d49bf04,0x3f80bf5c,0x3e163eac,0xbf7d3f71,0xbf4e3edb,0x3f18bf67,0x3f67bf18,0xbedb3f4e,0xbf713f7d,0xbeacbe16,
0x3f5cbf80,0x3f04bd49,0xbe793f2c,0xbf783f3e,0xbf0e3e48,0x3f55bf7b,0x3f0ebe48,0xbf553f7b,0xbf7b3f55,0x3e48bf0e,0x3f7bbf55,0xbe483f0e,
0xbf553f7b,0xbf0e3e48,0x3f55bf7b,0x3f0ebe48,0xbe483f0e,0xbf7b3f55,0x3e48bf0e,0x3f7bbf55,0x3f67bf7d,0x3edbbe16,0xbf713f4e,0x3eacbf18,
0x3f04bf3e,0x3f5cbf2c,0xbf783f80,0xbe79bd49,0xbd49be79,0x3f80bf78,0xbf2c3f5c,0xbf3e3f04,0xbf183eac,0x3f4ebf71,0xbe163edb,0xbf7d3f67,
0x3e95bdc9,0xbf753f7f,0x3f75bf7f,0x3e95bdc9,0x3f22bef1,0xbf463f62,0x3f46bf62,0x3f22bef1,0x3f62bf46,0xbef13f22,0x3ef1bf22,0x3f62bf46,
0x3f7fbf75,0xbdc93e95,0x3dc9be95,0x3f7fbf75,0xbf7d3f80,0xbe163d49,0xbf183f2c,0xbf4e3f3e,0xbf713f78,0xbeac3e79,0xbedb3f04,0xbf673f5c,
0xbf5c3f67,0xbf043edb,0xbe793eac,0xbf783f71,0xbf3e3f4e,0xbf2c3f18,0xbd493e16,0xbf803f7d,0x3f803f80,0xbf803f80,0x3f803f80,0xbf803f80,
0x3f803f80,0xbf803f80,0x3f803f80,0xbf803f80,0x3f803f80,0xbf803f80,0x3f803f80,0xbf803f80,0x3f803f80,0xbf803f80,0x3f803f80,0xbf803f80,
0xbf7dbf80,0x3e163d49,0xbf18bf2c,0x3f4e3f3e,0xbf71bf78,0x3eac3e79,0xbedbbf04,0x3f673f5c,0xbf5cbf67,0x3f043edb,0xbe79beac,0x3f783f71,
0xbf3ebf4e,0x3f2c3f18,0xbd49be16,0x3f803f7d,0x3f753f7f,0xbe95bdc9,0xbe95bdc9,0xbf75bf7f,0x3f463f62,0xbf22bef1,0xbf22bef1,0xbf46bf62,
0x3ef13f22,0xbf62bf46,0xbf62bf46,0xbef1bf22,0x3dc93e95,0xbf7fbf75,0xbf7fbf75,0xbdc9be95,0xbf67bf7d,0x3edb3e16,0x3f713f4e,0x3eac3f18,
0xbf04bf3e,0x3f5c3f2c,0x3f783f80,0xbe793d49,0x3d49be79,0x3f803f78,0x3f2c3f5c,0xbf3ebf04,0x3f183eac,0x3f4e3f71,0x3e163edb,0xbf7dbf67,
0x3f553f7b,0xbf0ebe48,0xbf55bf7b,0x3f0e3e48,0x3e483f0e,0xbf7bbf55,0xbe48bf0e,0x3f7b3f55,0xbf0ebe48,0xbf55bf7b,0x3f0e3e48,0x3f553f7b,
0xbf7bbf55,0xbe48bf0e,0x3f7b3f55,0x3e483f0e,0xbf3ebf78,0x3f2c3e79,0x3d493f04,0xbf80bf5c,0x3e16beac,0x3f7d3f71,0xbf4ebedb,0xbf18bf67,
0x3f673f18,0x3edb3f4e,0xbf71bf7d,0x3eacbe16,0x3f5c3f80,0xbf04bd49,0xbe79bf2c,0x3f783f3e,0x3f223f75,0xbf46be95,0x3f463e95,0x3f223f75,
0xbef13dc9,0xbf62bf7f,0x3f623f7f,0xbef13dc9,0xbf7fbf62,0x3dc9bef1,0xbdc93ef1,0xbf7fbf62,0xbe95bf46,0x3f753f22,0xbf75bf22,0xbe95bf46,
0xbf04bf71,0x3f5c3eac,0xbf78bf67,0x3e79bedb,0x3f3e3e16,0x3f2c3f7d,0x3d49bf18,0x3f803f4e,0x3f4e3f80,0xbf183d49,0x3f7d3f2c,0x3e163f3e,
0xbedb3e79,0xbf67bf78,0x3eac3f5c,0xbf71bf04,0x3ec43f6d,0xbf6dbec4,0x3ec43f6d,0xbf6dbec4,0xbf6dbec4,0xbec4bf6d,0xbf6dbec4,0xbec4bf6d,
0xbec4bf6d,0x3f6d3ec4,0xbec4bf6d,0x3f6d3ec4,0x3f6d3ec4,0x3ec43f6d,0x3f6d3ec4,0x3ec43f6d,0xbe79bf67,0x3f783edb,0x3f04beac,0x3f5c3f71,
0x3f803f18,0x3d493f4e,0x3f3e3f7d,0xbf2c3e16,0xbe163f2c,0xbf7dbf3e,0xbf4ebd49,0xbf18bf80,0xbf71bf5c,0x3eacbf04,0xbedbbf78,0x3f673e79,
0x3dc93f62,0xbf7fbef1,0xbf7fbef1,0xbdc9bf62,0xbf75bf46,0x3e95bf22,0x3e95bf22,0x3f753f46,0x3f22be95,0x3f463f75,0x3f463f75,0xbf223e95,
0x3ef13f7f,0xbf62bdc9,0xbf62bdc9,0xbef1bf7f,0x3d49bf5c,0x3f803f04,0x3f2c3f78,0xbf3e3e79,0x3f4e3f67,0xbf183edb,0xbf7dbeac,0xbe16bf71,
0xbf71be16,0xbeacbf7d,0x3edbbf18,0x3f673f4e,0x3e79bf3e,0x3f783f2c,0x3f043f80,0xbf5c3d49,0xbe483f55,0xbf7bbf0e,0x3e48bf55,0x3f7b3f0e,
0xbf0ebf7b,0x3f55be48,0x3f0e3f7b,0xbf553e48,0x3f7b3f0e,0xbe483f55,0xbf7bbf0e,0x3e48bf55,0xbf553e48,0xbf0ebf7b,0x3f55be48,0x3f0e3f7b,
0x3eacbf4e,0x3f713f18,0xbf673e16,0xbedbbf7d,0x3e793f80,0xbf78bd49,0x3f04bf2c,0x3f5c3f3e,0xbf3ebf5c,0x3f2cbf04,0x3d493f78,0xbf80be79,
0x3f7d3edb,0xbe163f67,0xbf18bf71,0x3f4ebeac,0xbef13f46,0xbf62bf22,0x3f623f22,0xbef13f46,0x3dc9bf75,0x3f7f3e95,0xbf7fbe95,0x3dc9bf75,
0x3e953f7f,0xbf753dc9,0x3f75bdc9,0x3e953f7f,0xbf22bf62,0x3f46bef1,0xbf463ef1,0xbf22bf62,0x3f18bf3e,0x3f4e3f2c,0xbe16bf80,0x3f7dbd49,
0xbedb3f5c,0xbf67bf04,0x3eac3f78,0xbf713e79,0x3e79bf71,0x3f783eac,0xbf04bf67,0x3f5cbedb,0xbd493f7d,0xbf80be16,0x3f2c3f4e,0xbf3e3f18,
0xbf353f35,0xbf35bf35,0xbf353f35,0xbf35bf35,0x3f35bf35,0x3f353f35,0x3f35bf35,0x3f353f35,0xbf353f35,0xbf35bf35,0xbf353f35,0xbf35bf35,
0x3f35bf35,0x3f353f35,0x3f35bf35,0x3f353f35,0x3f4ebf2c,0x3f183f3e,0x3f7d3d49,0xbe163f80,0xbf673f04,0xbedbbf5c,0xbf71be79,0x3eacbf78,
0x3f78beac,0x3e793f71,0x3f5c3edb,0xbf043f67,0xbf803e16,0xbd49bf7d,0xbf3ebf18,0x3f2cbf4e,0xbf623f22,0xbef1bf46,0xbef1bf46,0x3f62bf22,
0x3f7fbe95,0x3dc93f75,0x3dc93f75,0xbf7f3e95,0xbf75bdc9,0x3e95bf7f,0x3e95bf7f,0x3f753dc9,0x3f463ef1,0xbf223f62,0xbf223f62,0xbf46bef1,
0x3f71bf18,0x3eac3f4e,0xbedb3f7d,0xbf67be16,0xbf783d49,0x3e79bf80,0x3f5cbf3e,0x3f043f2c,0x3f2c3f04,0xbf3e3f5c,0xbf803e79,0x3d49bf78,
0xbe16bf67,0x3f7dbedb,0x3f4e3eac,0xbf183f71,0xbf7b3f0e,0xbe48bf55,0x3f7bbf0e,0x3e483f55,0x3f553e48,0xbf0e3f7b,0xbf55be48,0x3f0ebf7b,
0xbe48bf55,0x3f7bbf0e,0x3e483f55,0xbf7b3f0e,0xbf0e3f7b,0xbf55be48,0x3f0ebf7b,0x3f553e48,0x3f80bf04,0x3d493f5c,0xbf3ebe79,0x3f2cbf78,
0xbf18bedb,0x3f4ebf67,0xbe163f71,0xbf7d3eac,0xbeac3f7d,0xbf713e16,0x3f67bf4e,0x3edb3f18,0x3f78bf2c,0x3e793f3e,0xbf5cbd49,0x3f04bf80,
0xbf7f3ef1,0x3dc9bf62,0xbdc93f62,0xbf7f3ef1,0x3e953f22,0xbf753f46,0x3f75bf46,0x3e953f22,0x3f46bf75,0x3f223e95,0xbf22be95,0x3f46bf75,
0xbf623dc9,0x3ef1bf7f,0xbef13f7f,0xbf623dc9,0x3f78bedb,0xbe793f67,0x3f5cbf71,0x3f043eac,0x3d49bf4e,0x3f80bf18,0xbf2cbe16,0x3f3ebf7d,
0xbf7d3f3e,0xbe16bf2c,0xbf183f80,0xbf4e3d49,0x3eac3f04,0xbf713f5c,0x3f67be79,0xbedb3f78,0xbf6d3ec4,0x3ec4bf6d,0xbf6d3ec4,0x3ec4bf6d,
0xbec43f6d,0xbf6d3ec4,0xbec43f6d,0xbf6d3ec4,0x3f6dbec4,0xbec43f6d,0x3f6dbec4,0xbec43f6d,0x3ec4bf6d,0x3f6dbec4,0x3ec4bf6d,0x3f6dbec4,
0x3f5cbeac,0xbf043f71,0x3e793edb,0xbf783f67,0x3f2cbf7d,0x3f3ebe16,0x3f80bf4e,0x3d493f18,0xbf18bd49,0x3f4ebf80,0x3e16bf3e,0x3f7dbf2c,
0xbf673f78,0xbedbbe79,0xbf713f04,0x3eacbf5c,0xbf463e95,0x3f22bf75,0x3f22bf75,0x3f46be95,0xbf623f7f,0xbef1bdc9,0xbef1bdc9,0x3f62bf7f,
0x3dc93ef1,0xbf7f3f62,0xbf7f3f62,0xbdc9bef1,0x3f75bf22,0xbe953f46,0xbe953f46,0xbf753f22,0x3f2cbe79,0xbf3e3f78,0xbf803f5c,0x3d49bf04,
0x3f7dbf71,0x3e163eac,0xbf183f67,0xbf4e3edb,0x3edbbf4e,0x3f67bf18,0x3eac3e16,0xbf713f7d,0xbf043d49,0x3f5cbf80,0x3f78bf3e,0xbe793f2c,
0xbf0e3e48,0x3f55bf7b,0x3f0ebe48,0xbf553f7b,0xbf7b3f55,0x3e48bf0e,0x3f7bbf55,0xbe483f0e,0xbf553f7b,0xbf0e3e48,0x3f55bf7b,0x3f0ebe48,
0xbe483f0e,0xbf7b3f55,0x3e48bf0e,0x3f7bbf55,0x3edbbe16,0xbf673f7d,0x3eacbf18,0x3f71bf4e,0x3f5cbf2c,0xbf043f3e,0xbe79bd49,0x3f78bf80,
0x3f80bf78,0x3d493e79,0xbf3e3f04,0x3f2cbf5c,0x3f4ebf71,0x3f18beac,0xbf7d3f67,0x3e16bedb,0xbe953dc9,0x3f75bf7f,0xbf753f7f,0xbe953dc9,
0xbf223ef1,0x3f46bf62,0xbf463f62,0xbf223ef1,0xbf623f46,0x3ef1bf22,0xbef13f22,0xbf623f46,0xbf7f3f75,0x3dc9be95,0xbdc93e95,0xbf7f3f75,
0x3e16bd49,0xbf7d3f80,0x3f4ebf3e,0xbf183f2c,0x3eacbe79,0xbf713f78,0x3f67bf5c,0xbedb3f04,0x3f04bedb,0xbf5c3f67,0x3f78bf71,0xbe793eac,
0x3f2cbf18,0xbf3e3f4e,0x3f80bf7d,0xbd493e16,0x3f803f80,0xbf803f80,0x3f803f80,0xbf803f80,0x3f803f80,0xbf803f80,0x3f803f80,0xbf803f80,
0x3f803f80,0xbf803f80,0x3f803f80,0xbf803f80,0x3f803f80,0xbf803f80,0x3f803f80,0xbf803f80,0x3e163d49,0x3f7d3f80,0x3f4e3f3e,0x3f183f2c,
0x3eac3e79,0x3f713f78,0x3f673f5c,0x3edb3f04,0x3f043edb,0x3f5c3f67,0x3f783f71,0x3e793eac,0x3f2c3f18,0x3f3e3f4e,0x3f803f7d,0x3d493e16,
0xbf75bf7f,0x3e953dc9,0x3e953dc9,0x3f753f7f,0xbf46bf62,0x3f223ef1,0x3f223ef1,0x3f463f62,0xbef1bf22,0x3f623f46,0x3f623f46,0x3ef13f22,
0xbdc9be95,0x3f7f3f75,0x3f7f3f75,0x3dc93e95,0xbedbbe16,0xbf67bf7d,0xbeacbf18,0x3f713f4e,0xbf5cbf2c,0xbf04bf3e,0x3e79bd49,0x3f783f80,
0xbf80bf78,0x3d49be79,0x3f3e3f04,0x3f2c3f5c,0xbf4ebf71,0x3f183eac,0x3f7d3f67,0x3e163edb,0x3f553f7b,0xbf0ebe48,0xbf55bf7b,0x3f0e3e48,
0x3e483f0e,0xbf7bbf55,0xbe48bf0e,0x3f7b3f55,0xbf0ebe48,0xbf55bf7b,0x3f0e3e48,0x3f553f7b,0xbf7bbf55,0xbe48bf0e,0x3f7b3f55,0x3e483f0e,
0x3f2c3e79,0x3f3e3f78,0xbf80bf5c,0xbd49bf04,0x3f7d3f71,0xbe163eac,0xbf18bf67,0x3f4e3edb,0x3edb3f4e,0xbf67bf18,0x3eacbe16,0x3f713f7d,
0xbf04bd49,0xbf5cbf80,0x3f783f3e,0x3e793f2c,0xbf22bf75,0x3f463e95,0xbf46be95,0xbf22bf75,0x3ef1bdc9,0x3f623f7f,0xbf62bf7f,0x3ef1bdc9,
0x3f7f3f62,0xbdc93ef1,0x3dc9bef1,0x3f7f3f62,0x3e953f46,0xbf75bf22,0x3f753f22,0x3e953f46,0xbf5cbeac,0xbf04bf71,0xbe793edb,0xbf78bf67,
0xbf2cbf7d,0x3f3e3e16,0xbf80bf4e,0x3d49bf18,0x3f18bd49,0x3f4e3f80,0xbe16bf3e,0x3f7d3f2c,0x3f673f78,0xbedb3e79,0x3f713f04,0x3eac3f5c,
0x3ec43f6d,0xbf6dbec4,0x3ec43f6d,0xbf6dbec4,0xbf6dbec4,0xbec4bf6d,0xbf6dbec4,0xbec4bf6d,0xbec4bf6d,0x3f6d3ec4,0xbec4bf6d,0x3f6d3ec4,
0x3f6d3ec4,0x3ec43f6d,0x3f6d3ec4,0x3ec43f6d,0x3f783edb,0x3e793f67,0x3f5c3f71,0xbf043eac,0x3d493f4e,0xbf80bf18,0xbf2c3e16,0xbf3ebf7d,
0xbf7dbf3e,0x3e16bf2c,0xbf18bf80,0x3f4e3d49,0x3eacbf04,0x3f713f5c,0x3f673e79,0x3edb3f78,0xbdc9bf62,0x3f7f3ef1,0x3f7f3ef1,0x3dc93f62,
0x3f753f46,0xbe953f22,0xbe953f22,0xbf75bf46,0xbf223e95,0xbf46bf75,0xbf46bf75,0x3f22be95,0xbef1bf7f,0x3f623dc9,0x3f623dc9,0x3ef13f7f,
0xbf80bf04,0x3d49bf5c,0x3f3ebe79,0x3f2c3f78,0x3f18bedb,0x3f4e3f67,0x3e163f71,0xbf7dbeac,0x3eac3f7d,0xbf71be16,0xbf67bf4e,0x3edbbf18,
0xbf78bf2c,0x3e79bf3e,0x3f5cbd49,0x3f043f80,0xbe483f55,0xbf7bbf0e,0x3e48bf55,0x3f7b3f0e,0xbf0ebf7b,0x3f55be48,0x3f0e3f7b,0xbf553e48,
0x3f7b3f0e,0xbe483f55,0xbf7bbf0e,0x3e48bf55,0xbf553e48,0xbf0ebf7b,0x3f55be48,0x3f0e3f7b,0x3f713f18,0xbeac3f4e,0xbedbbf7d,0x3f67be16,
0xbf78bd49,0xbe79bf80,0x3f5c3f3e,0xbf043f2c,0x3f2cbf04,0x3f3e3f5c,0xbf80be79,0xbd49bf78,0xbe163f67,0xbf7dbedb,0x3f4ebeac,0x3f183f71,
0x3ef1bf46,0x3f623f22,0xbf62bf22,0x3ef1bf46,0xbdc93f75,0xbf7fbe95,0x3f7f3e95,0xbdc93f75,0xbe95bf7f,0x3f75bdc9,0xbf753dc9,0xbe95bf7f,
0x3f223f62,0xbf463ef1,0x3f46bef1,0x3f223f62,0xbf4ebf2c,0x3f18bf3e,0xbf7d3d49,0xbe16bf80,0x3f673f04,0xbedb3f5c,0x3f71be79,0x3eac3f78,
0xbf78beac,0x3e79bf71,0xbf5c3edb,0xbf04bf67,0x3f803e16,0xbd493f7d,0x3f3ebf18,0x3f2c3f4e,0xbf353f35,0xbf35bf35,0xbf353f35,0xbf35bf35,
0x3f35bf35,0x3f353f35,0x3f35bf35,0x3f353f35,0xbf353f35,0xbf35bf35,0xbf353f35,0xbf35bf35,0x3f35bf35,0x3f353f35,0x3f35bf35,0x3f353f35,
0x3f183f3e,0xbf4e3f2c,0xbe163f80,0xbf7dbd49,0xbedbbf5c,0x3f67bf04,0x3eacbf78,0x3f713e79,0x3e793f71,0xbf783eac,0xbf043f67,0xbf5cbedb,
0xbd49bf7d,0x3f80be16,0x3f2cbf4e,0x3f3e3f18,0x3f62bf22,0x3ef13f46,0x3ef13f46,0xbf623f22,0xbf7f3e95,0xbdc9bf75,0xbdc9bf75,0x3f7fbe95,
0x3f753dc9,0xbe953f7f,0xbe953f7f,0xbf75bdc9,0xbf46bef1,0x3f22bf62,0x3f22bf62,0x3f463ef1,0xbeacbf4e,0x3f71bf18,0x3f673e16,0xbedb3f7d,
0xbe793f80,0xbf783d49,0xbf04bf2c,0x3f5cbf3e,0x3f3ebf5c,0x3f2c3f04,0xbd493f78,0xbf803e79,0xbf7d3edb,0xbe16bf67,0x3f18bf71,0x3f4e3eac,
0xbf7b3f0e,0xbe48bf55,0x3f7bbf0e,0x3e483f55,0x3f553e48,0xbf0e3f7b,0xbf55be48,0x3f0ebf7b,0xbe48bf55,0x3f7bbf0e,0x3e483f55,0xbf7b3f0e,
0xbf0e3f7b,0xbf55be48,0x3f0ebf7b,0x3f553e48,0x3d493f5c,0xbf803f04,0x3f2cbf78,0x3f3e3e79,0x3f4ebf67,0x3f183edb,0xbf7d3eac,0x3e16bf71,
0xbf713e16,0x3eacbf7d,0x3edb3f18,0xbf673f4e,0x3e793f3e,0xbf783f2c,0x3f04bf80,0x3f5c3d49,0x3f7fbef1,0xbdc93f62,0x3dc9bf62,0x3f7fbef1,
0xbe95bf22,0x3f75bf46,0xbf753f46,0xbe95bf22,0xbf463f75,0xbf22be95,0x3f223e95,0xbf463f75,0x3f62bdc9,0xbef13f7f,0x3ef1bf7f,0x3f62bdc9,
0x3e79bf67,0x3f78bedb,0xbf04beac,0x3f5cbf71,0xbf803f18,0x3d49bf4e,0xbf3e3f7d,0xbf2cbe16,0x3e163f2c,0xbf7d3f3e,0x3f4ebd49,0xbf183f80,
0x3f71bf5c,0x3eac3f04,0x3edbbf78,0x3f67be79,0xbf6d3ec4,0x3ec4bf6d,0xbf6d3ec4,0x3ec4bf6d,0xbec43f6d,0xbf6d3ec4,0xbec43f6d,0xbf6d3ec4,
0x3f6dbec4,0xbec43f6d,0x3f6dbec4,0xbec43f6d,0x3ec4bf6d,0x3f6dbec4,0x3ec4bf6d,0x3f6dbec4,0xbf043f71,0xbf5c3eac,0xbf783f67,0xbe79bedb,
0x3f3ebe16,0xbf2c3f7d,0x3d493f18,0xbf803f4e,0x3f4ebf80,0x3f183d49,0x3f7dbf2c,0xbe163f3e,0xbedbbe79,0x3f67bf78,0x3eacbf5c,0x3f71bf04,
0x3f46be95,0xbf223f75,0xbf223f75,0xbf463e95,0x3f62bf7f,0x3ef13dc9,0x3ef13dc9,0xbf623f7f,0xbdc9bef1,0x3f7fbf62,0x3f7fbf62,0x3dc93ef1,
0xbf753f22,0x3e95bf46,0x3e95bf46,0x3f75bf22,0x3f3ebf78,0x3f2cbe79,0xbd493f04,0xbf803f5c,0xbe16beac,0x3f7dbf71,0x3f4ebedb,0xbf183f67,
0xbf673f18,0x3edbbf4e,0x3f71bf7d,0x3eac3e16,0xbf5c3f80,0xbf043d49,0x3e79bf2c,0x3f78bf3e,0xbf0e3e48,0x3f55bf7b,0x3f0ebe48,0xbf553f7b,
0xbf7b3f55,0x3e48bf0e,0x3f7bbf55,0xbe483f0e,0xbf553f7b,0xbf0e3e48,0x3f55bf7b,0x3f0ebe48,0xbe483f0e,0xbf7b3f55,0x3e48bf0e,0x3f7bbf55,
0xbf673f7d,0xbedb3e16,0x3f71bf4e,0xbeac3f18,0xbf043f3e,0xbf5c3f2c,0x3f78bf80,0x3e793d49,0x3d493e79,0xbf803f78,0x3f2cbf5c,0x3f3ebf04,
0x3f18beac,0xbf4e3f71,0x3e16bedb,0x3f7dbf67,0x3e95bdc9,0xbf753f7f,0x3f75bf7f,0x3e95bdc9,0x3f22bef1,0xbf463f62,0x3f46bf62,0x3f22bef1,
0x3f62bf46,0xbef13f22,0x3ef1bf22,0x3f62bf46,0x3f7fbf75,0xbdc93e95,0x3dc9be95,0x3f7fbf75,0x3f7dbf80,0x3e16bd49,0x3f18bf2c,0x3f4ebf3e,
0x3f71bf78,0x3eacbe79,0x3edbbf04,0x3f67bf5c,0x3f5cbf67,0x3f04bedb,0x3e79beac,0x3f78bf71,0x3f3ebf4e,0x3f2cbf18,0x3d49be16,0x3f80bf7d,
0x3f803f80,0xbf353f35,0x3f803f80,0xbf353f35,0x3f803f80,0xbf353f35,0x3f803f80,0xbf353f35,0x3f803f80,0xbf353f35,0x3f803f80,0xbf353f35,
0x3f803f80,0xbf353f35,0x3f803f80,0xbf353f35,0x3f7c3f7f,0xbe2fbd97,0x3f133f27,0xbf51bf42,0x3f6f3f77,0xbeb8be89,0x3ecf3efc,0xbf6abf5f,
0x3f583f65,0xbf09bee6,0x3e603ea1,0xbf7abf73,0x3f393f4a,0xbf31bf1d,0x3cc93dfb,0xbf80bf7e,0x3f713f7d,0xbeacbe16,0xbeacbe16,0xbf71bf7d,
0x3f3e3f5c,0xbf2cbf04,0xbf2cbf04,0xbf3ebf5c,0x3edb3f18,0xbf67bf4e,0xbf67bf4e,0xbedbbf18,0x3d493e79,0xbf80bf78,0xbf80bf78,0xbd49be79,
0x3f5f3f7a,0xbefcbe60,0xbf77bf58,0xbe89bf09,0x3ee63f31,0xbf65bf39,0xbf73bf80,0x3ea13cc9,0xbdfb3e2f,0xbf7ebf7c,0xbf1dbf51,0x3f4a3f13,
0xbf27becf,0xbf42bf6a,0xbd97beb8,0x3f7f3f6f,0x3f463f75,0xbf22be95,0xbf46bf75,0x3f223e95,0x3dc93ef1,0xbf7fbf62,0xbdc9bef1,0x3f7f3f62,
0xbf22be95,0xbf46bf75,0x3f223e95,0x3f463f75,0xbf7fbf62,0xbdc9bef1,0x3f7f3f62,0x3dc93ef1,0x3f273f6f,0xbf42beb8,0x3d97becf,0x3f7f3f6a,
0xbe893e60,0xbf77bf7a,0x3f5f3f09,0x3efc3f58,0xbf73bf31,0xbea1bf39,0x3f653f80,0xbee63cc9,0xbf4abf7c,0x3f1d3e2f,0x3dfb3f13,0xbf7ebf51,
0x3f043f67,0xbf5cbedb,0x3f5c3edb,0x3f043f67,0xbf18bd49,0xbf4ebf80,0x3f4e3f80,0xbf18bd49,0xbf78bf71,0x3e79beac,0xbe793eac,0xbf78bf71,
0xbe16bf2c,0x3f7d3f3e,0xbf7dbf3e,0xbe16bf2c,0x3eb83f5f,0xbf6fbefc,0x3f6a3f77,0xbecf3e89,0xbf58bea1,0xbf09bf73,0xbe603ee6,0xbf7abf65,
0xbf31bf7e,0x3f393dfb,0xbf80bf4a,0x3cc9bf1d,0x3f13bd97,0x3f513f7f,0xbe2fbf42,0x3f7c3f27,0x3e483f55,0xbf7bbf0e,0x3e483f55,0xbf7bbf0e,
0xbf7bbf0e,0xbe48bf55,0xbf7bbf0e,0xbe48bf55,0xbe48bf55,0x3f7b3f0e,0xbe48bf55,0x3f7b3f0e,0x3f7b3f0e,0x3e483f55,0x3f7b3f0e,0x3e483f55,
0x3cc93f4a,0xbf80bf1d,0xbf313dfb,0xbf39bf7e,0xbf7cbf42,0x3e2fbf27,0xbf13bf7f,0x3f513d97,0x3eb8befc,0x3f6f3f5f,0x3f6a3e89,0x3ecf3f77,
0x3f583f73,0xbf093ea1,0x3e603f65,0xbf7abee6,0xbe163f3e,0xbf7dbf2c,0xbf7dbf2c,0x3e16bf3e,0xbf5cbf67,0x3f04bedb,0x3f04bedb,0x3f5c3f67,
0x3f4ebd49,0x3f183f80,0x3f183f80,0xbf4e3d49,0x3e793f71,0xbf78beac,0xbf78beac,0xbe79bf71,0xbea13f31,0xbf73bf39,0xbee6bf80,0x3f653cc9,
0xbf1dbf7c,0x3f4abe2f,0x3f7e3f13,0xbdfb3f51,0x3f7f3ecf,0x3d973f6a,0xbf273eb8,0xbf42bf6f,0xbefc3f09,0xbf5fbf58,0xbe89bf7a,0x3f773e60,
0xbef13f22,0xbf62bf46,0x3ef1bf22,0x3f623f46,0xbe95bf7f,0x3f753dc9,0x3e953f7f,0xbf75bdc9,0x3f623f46,0xbef13f22,0xbf62bf46,0x3ef1bf22,
0xbf75bdc9,0xbe95bf7f,0x3f753dc9,0x3e953f7f,0xbf1d3f13,0xbf4abf51,0x3f7e3e2f,0x3dfb3f7c,0x3d97bf6f,0x3f7f3eb8,0xbf423ecf,0xbf27bf6a,
0x3efc3f7a,0xbf5f3e60,0x3e89bf58,0x3f773f09,0xbf65bf31,0x3ee6bf39,0x3ea13f80,0xbf733cc9,0xbf3e3f04,0xbf2cbf5c,0x3f2c3f5c,0xbf3e3f04,
0x3edbbf4e,0x3f673f18,0xbf67bf18,0x3edbbf4e,0xbd493f78,0xbf80be79,0x3f803e79,0xbd493f78,0xbeacbf7d,0x3f71be16,0xbf713e16,0xbeacbf7d,
0xbf583ee6,0xbf09bf65,0xbe603f73,0xbf7abea1,0x3f39bf1d,0x3f313f4a,0x3cc9bf7e,0x3f803dfb,0xbf133f42,0xbf51bf27,0x3e2f3f7f,0xbf7c3d97,
0x3ecfbf5f,0x3f6a3efc,0xbeb8bf77,0x3f6fbe89,0xbf6d3ec4,0xbec4bf6d,0xbf6d3ec4,0xbec4bf6d,0x3f6dbec4,0x3ec43f6d,0x3f6dbec4,0x3ec43f6d,
0xbf6d3ec4,0xbec4bf6d,0xbf6d3ec4,0xbec4bf6d,0x3f6dbec4,0x3ec43f6d,0x3f6dbec4,0x3ec43f6d,0xbf7a3ea1,0xbe60bf73,0xbf58bee6,0x3f09bf65,
0x3f80bdfb,0x3cc93f7e,0x3f393f1d,0xbf313f4a,0xbf7cbd97,0x3e2fbf7f,0xbf13bf42,0x3f51bf27,0x3f6f3e89,0xbeb83f77,0x3ecf3f5f,0xbf6a3efc,
0xbf803e79,0xbd49bf78,0xbd49bf78,0x3f80be79,0x3f713e16,0xbeac3f7d,0xbeac3f7d,0xbf71be16,0xbf3ebf04,0x3f2cbf5c,0x3f2cbf5c,0x3f3e3f04,
0x3edb3f4e,0xbf673f18,0xbf673f18,0xbedbbf4e,0xbf7e3e2f,0x3dfbbf7c,0x3f4abf51,0x3f1d3f13,0x3f423ecf,0xbf273f6a,0xbf7f3eb8,0xbd97bf6f,
0xbe89bf58,0x3f77bf09,0x3f5f3e60,0xbefc3f7a,0xbea13f80,0xbf73bcc9,0xbee6bf39,0x3f65bf31,0xbf753dc9,0x3e95bf7f,0x3f75bdc9,0xbe953f7f,
0x3ef13f22,0xbf623f46,0xbef1bf22,0x3f62bf46,0x3e95bf7f,0x3f75bdc9,0xbe953f7f,0xbf753dc9,0xbf623f46,0xbef1bf22,0x3f62bf46,0x3ef13f22,
0xbf653cc9,0x3ee6bf80,0x3ea13f31,0xbf733f39,0x3dfb3f51,0xbf7e3f13,0x3f1dbf7c,0x3f4a3e2f,0x3f42bf6f,0x3f273eb8,0xbf7f3ecf,0x3d97bf6a,
0xbf773e60,0x3e89bf7a,0x3efc3f09,0xbf5f3f58,0xbf4ebd49,0x3f18bf80,0xbf183f80,0xbf4ebd49,0xbe793f71,0xbf783eac,0x3f78beac,0xbe793f71,
0x3f7dbf2c,0x3e163f3e,0xbe16bf3e,0x3f7dbf2c,0xbf04bedb,0x3f5cbf67,0xbf5c3f67,0xbf04bedb,0xbf31bdfb,0x3f39bf7e,0xbf803f1d,0x3cc9bf4a,
0xbf133f7f,0xbf513d97,0x3e2f3f27,0xbf7c3f42,0x3f6abe89,0xbecf3f77,0x3f6fbf5f,0x3eb83efc,0x3e60bf65,0x3f7abee6,0xbf09bea1,0x3f58bf73,
0xbf0ebe48,0x3f55bf7b,0xbf0ebe48,0x3f55bf7b,0xbf553f7b,0xbf0ebe48,0xbf553f7b,0xbf0ebe48,0x3f0e3e48,0xbf553f7b,0x3f0e3e48,0xbf553f7b,
0x3f55bf7b,0x3f0e3e48,0x3f55bf7b,0x3f0e3e48,0xbecfbe89,0x3f6abf77,0x3eb8bf5f,0x3f6fbefc,0xbf7a3f65,0xbe60bee6,0xbf583ea1,0x3f09bf73,
0x3cc93f1d,0xbf803f4a,0xbf313f7e,0xbf393dfb,0x3f7cbf27,0xbe2f3f42,0x3f133d97,0xbf513f7f,0xbe79beac,0x3f78bf71,0x3f78bf71,0x3e793eac,
0xbf7d3f3e,0x3e16bf2c,0x3e16bf2c,0x3f7dbf3e,0xbf043f67,0xbf5c3edb,0xbf5c3edb,0x3f04bf67,0x3f18bd49,0xbf4e3f80,0xbf4e3f80,0xbf183d49,
0xbd97becf,0x3f7fbf6a,0x3f42beb8,0xbf273f6f,0xbf5f3f09,0x3efcbf58,0x3f77bf7a,0x3e893e60,0xbf653f80,0xbee6bcc9,0x3ea1bf39,0x3f73bf31,
0xbdfb3f13,0xbf7e3f51,0xbf1d3e2f,0x3f4abf7c,0x3dc9bef1,0x3f7fbf62,0xbdc93ef1,0xbf7f3f62,0xbf223e95,0x3f46bf75,0x3f22be95,0xbf463f75,
0xbf7f3f62,0x3dc9bef1,0x3f7fbf62,0xbdc93ef1,0xbf463f75,0xbf223e95,0x3f46bf75,0x3f22be95,0x3e89bf09,0x3f77bf58,0xbf5f3f7a,0xbefc3e60,
0xbea13cc9,0x3f73bf80,0xbee63f31,0xbf653f39,0xbf4a3f13,0x3f1dbf51,0x3dfb3e2f,0xbf7e3f7c,0xbf7f3f6f,0x3d97beb8,0x3f27becf,0xbf423f6a,
0x3edbbf18,0x3f67bf4e,0xbf673f4e,0x3edbbf18,0x3d49be79,0x3f80bf78,0xbf803f78,0x3d49be79,0xbeac3e16,0x3f71bf7d,0xbf713f7d,0xbeac3e16,
0xbf2c3f04,0x3f3ebf5c,0xbf3e3f5c,0xbf2c3f04,0x3f13bf27,0x3f51bf42,0xbe2f3d97,0x3f7cbf7f,0x3ecfbefc,0x3f6abf5f,0xbeb83e89,0x3f6fbf77,
0x3e60bea1,0x3f7abf73,0xbf093ee6,0x3f58bf65,0x3cc9bdfb,0x3f80bf7e,0xbf313f1d,0x3f39bf4a,0x3f803f80,0xbf353f35,0x3f803f80,0xbf353f35,
0x3f803f80,0xbf353f35,0x3f803f80,0xbf353f35,0x3f803f80,0xbf353f35,0x3f803f80,0xbf353f35,0x3f803f80,0xbf353f35,0x3f803f80,0xbf353f35,
0xbe2fbd97,0xbf7cbf7f,0xbf51bf42,0xbf13bf27,0xbeb8be89,0xbf6fbf77,0xbf6abf5f,0xbecfbefc,0xbf09bee6,0xbf58bf65,0xbf7abf73,0xbe60bea1,
0xbf31bf1d,0xbf39bf4a,0xbf80bf7e,0xbcc9bdfb,0xbf71bf7d,0x3eac3e16,0x3eac3e16,0x3f713f7d,0xbf3ebf5c,0x3f2c3f04,0x3f2c3f04,0x3f3e3f5c,
0xbedbbf18,0x3f673f4e,0x3f673f4e,0x3edb3f18,0xbd49be79,0x3f803f78,0x3f803f78,0x3d493e79,0x3efc3e60,0x3f5f3f7a,0x3e893f09,0xbf77bf58,
0x3f653f39,0x3ee63f31,0xbea1bcc9,0xbf73bf80,0x3f7e3f7c,0xbdfb3e2f,0xbf4abf13,0xbf1dbf51,0x3f423f6a,0xbf27becf,0xbf7fbf6f,0xbd97beb8,
0x3f463f75,0xbf22be95,0xbf46bf75,0x3f223e95,0x3dc93ef1,0xbf7fbf62,0xbdc9bef1,0x3f7f3f62,0xbf22be95,0xbf46bf75,0x3f223e95,0x3f463f75,
0xbf7fbf62,0xbdc9bef1,0x3f7f3f62,0x3dc93ef1,0xbf42beb8,0xbf27bf6f,0x3f7f3f6a,0xbd973ecf,0xbf77bf7a,0x3e89be60,0x3efc3f58,0xbf5fbf09,
0xbea1bf39,0x3f733f31,0xbee63cc9,0xbf65bf80,0x3f1d3e2f,0x3f4a3f7c,0xbf7ebf51,0xbdfbbf13,0xbf04bf67,0x3f5c3edb,0xbf5cbedb,0xbf04bf67,
0x3f183d49,0x3f4e3f80,0xbf4ebf80,0x3f183d49,0x3f783f71,0xbe793eac,0x3e79beac,0x3f783f71,0x3e163f2c,0xbf7dbf3e,0x3f7d3f3e,0x3e163f2c,
0x3f6f3efc,0x3eb83f5f,0x3ecfbe89,0x3f6a3f77,0x3f093f73,0xbf58bea1,0x3f7a3f65,0xbe603ee6,0xbf39bdfb,0xbf31bf7e,0xbcc93f1d,0xbf80bf4a,
0xbf51bf7f,0x3f13bd97,0xbf7cbf27,0xbe2fbf42,0x3e483f55,0xbf7bbf0e,0x3e483f55,0xbf7bbf0e,0xbf7bbf0e,0xbe48bf55,0xbf7bbf0e,0xbe48bf55,
0xbe48bf55,0x3f7b3f0e,0xbe48bf55,0x3f7b3f0e,0x3f7b3f0e,0x3e483f55,0x3f7b3f0e,0x3e483f55,0xbf80bf1d,0xbcc9bf4a,0xbf39bf7e,0x3f31bdfb,
0x3e2fbf27,0x3f7c3f42,0x3f513d97,0x3f133f7f,0x3f6f3f5f,0xbeb83efc,0x3ecf3f77,0xbf6abe89,0xbf093ea1,0xbf58bf73,0xbf7abee6,0xbe60bf65,
0x3e16bf3e,0x3f7d3f2c,0x3f7d3f2c,0xbe163f3e,0x3f5c3f67,0xbf043edb,0xbf043edb,0xbf5cbf67,0xbf4e3d49,0xbf18bf80,0xbf18bf80,0x3f4ebd49,
0xbe79bf71,0x3f783eac,0x3f783eac,0x3e793f71,0x3f733f39,0xbea13f31,0xbf65bcc9,0xbee6bf80,0xbf4a3e2f,0xbf1dbf7c,0x3dfbbf51,0x3f7e3f13,
0xbd97bf6a,0x3f7f3ecf,0x3f423f6f,0xbf273eb8,0x3f5f3f58,0xbefc3f09,0xbf77be60,0xbe89bf7a,0xbef13f22,0xbf62bf46,0x3ef1bf22,0x3f623f46,
0xbe95bf7f,0x3f753dc9,0x3e953f7f,0xbf75bdc9,0x3f623f46,0xbef13f22,0xbf62bf46,0x3ef1bf22,0xbf75bdc9,0xbe95bf7f,0x3f753dc9,0x3e953f7f,
0xbf4abf51,0x3f1dbf13,0x3dfb3f7c,0xbf7ebe2f,0x3f7f3eb8,0xbd973f6f,0xbf27bf6a,0x3f42becf,0xbf5f3e60,0xbefcbf7a,0x3f773f09,0xbe893f58,
0x3ee6bf39,0x3f653f31,0xbf733cc9,0xbea1bf80,0x3f3ebf04,0x3f2c3f5c,0xbf2cbf5c,0x3f3ebf04,0xbedb3f4e,0xbf67bf18,0x3f673f18,0xbedb3f4e,
0x3d49bf78,0x3f803e79,0xbf80be79,0x3d49bf78,0x3eac3f7d,0xbf713e16,0x3f71be16,0x3eac3f7d,0x3f093f65,0xbf583ee6,0x3f7a3ea1,0xbe603f73,
0xbf31bf4a,0x3f39bf1d,0xbf80bdfb,0x3cc9bf7e,0x3f513f27,0xbf133f42,0x3f7cbd97,0x3e2f3f7f,0xbf6abefc,0x3ecfbf5f,0xbf6f3e89,0xbeb8bf77,
0xbf6d3ec4,0xbec4bf6d,0xbf6d3ec4,0xbec4bf6d,0x3f6dbec4,0x3ec43f6d,0x3f6dbec4,0x3ec43f6d,0xbf6d3ec4,0xbec4bf6d,0xbf6d3ec4,0xbec4bf6d,
0x3f6dbec4,0x3ec43f6d,0x3f6dbec4,0x3ec43f6d,0xbe60bf73,0x3f7abea1,0x3f09bf65,0x3f583ee6,0x3cc93f7e,0xbf803dfb,0xbf313f4a,0xbf39bf1d,
0x3e2fbf7f,0x3f7c3d97,0x3f51bf27,0x3f133f42,0xbeb83f77,0xbf6fbe89,0xbf6a3efc,0xbecfbf5f,0x3f80be79,0x3d493f78,0x3d493f78,0xbf803e79,
0xbf71be16,0x3eacbf7d,0x3eacbf7d,0x3f713e16,0x3f3e3f04,0xbf2c3f5c,0xbf2c3f5c,0xbf3ebf04,0xbedbbf4e,0x3f67bf18,0x3f67bf18,0x3edb3f4e,
0xbdfb3f7c,0xbf7e3e2f,0xbf1dbf13,0x3f4abf51,0x3f27bf6a,0x3f423ecf,0x3d973f6f,0xbf7f3eb8,0xbf773f09,0xbe89bf58,0x3efcbf7a,0x3f5f3e60,
0x3f733cc9,0xbea13f80,0xbf653f31,0xbee6bf39,0xbf753dc9,0x3e95bf7f,0x3f75bdc9,0xbe953f7f,0x3ef13f22,0xbf623f46,0xbef1bf22,0x3f62bf46,
0x3e95bf7f,0x3f75bdc9,0xbe953f7f,0xbf753dc9,0xbf623f46,0xbef1bf22,0x3f62bf46,0x3ef13f22,0x3ee6bf80,0x3f65bcc9,0xbf733f39,0xbea1bf31,
0xbf7e3f13,0xbdfbbf51,0x3f4a3e2f,0xbf1d3f7c,0x3f273eb8,0xbf423f6f,0x3d97bf6a,0x3f7fbecf,0x3e89bf7a,0x3f77be60,0xbf5f3f58,0xbefcbf09,
0x3f4e3d49,0xbf183f80,0x3f18bf80,0x3f4e3d49,0x3e79bf71,0x3f78beac,0xbf783eac,0x3e79bf71,0xbf7d3f2c,0xbe16bf3e,0x3e163f3e,0xbf7d3f2c,
0x3f043edb,0xbf5c3f67,0x3f5cbf67,0x3f043edb,0xbf393f7e,0xbf31bdfb,0xbcc93f4a,0xbf803f1d,0x3f51bd97,0xbf133f7f,0x3f7cbf42,0x3e2f3f27,
0x3ecfbf77,0x3f6abe89,0xbeb8befc,0x3f6fbf5f,0xbf7a3ee6,0x3e60bf65,0xbf583f73,0xbf09bea1,0xbf0ebe48,0x3f55bf7b,0xbf0ebe48,0x3f55bf7b,
0xbf553f7b,0xbf0ebe48,0xbf553f7b,0xbf0ebe48,0x3f0e3e48,0xbf553f7b,0x3f0e3e48,0xbf553f7b,0x3f55bf7b,0x3f0e3e48,0x3f55bf7b,0x3f0e3e48,
0x3f6abf77,0x3ecf3e89,0x3f6fbefc,0xbeb83f5f,0xbe60bee6,0x3f7abf65,0x3f09bf73,0x3f58bea1,0xbf803f4a,0xbcc9bf1d,0xbf393dfb,0x3f31bf7e,
0xbe2f3f42,0xbf7c3f27,0xbf513f7f,0xbf13bd97,0x3e793eac,0xbf783f71,0xbf783f71,0xbe79beac,0x3f7dbf3e,0xbe163f2c,0xbe163f2c,0xbf7d3f3e,
0x3f04bf67,0x3f5cbedb,0x3f5cbedb,0xbf043f67,0xbf183d49,0x3f4ebf80,0x3f4ebf80,0x3f18bd49,0xbf7f3f6a,0xbd97becf,0x3f27bf6f,0x3f42beb8,
0xbefc3f58,0xbf5f3f09,0xbe89be60,0x3f77bf7a,0x3ee63cc9,0xbf653f80,0xbf733f31,0x3ea1bf39,0x3f7ebf51,0xbdfb3f13,0xbf4a3f7c,0xbf1d3e2f,
0x3dc9bef1,0x3f7fbf62,0xbdc93ef1,0xbf7f3f62,0xbf223e95,0x3f46bf75,0x3f22be95,0xbf463f75,0xbf7f3f62,0x3dc9bef1,0x3f7fbf62,0xbdc93ef1,
0xbf463f75,0xbf223e95,0x3f46bf75,0x3f22be95,0x3f77bf58,0xbe893f09,0xbefc3e60,0x3f5fbf7a,0x3f73bf80,0x3ea1bcc9,0xbf653f39,0x3ee6bf31,
0x3f1dbf51,0x3f4abf13,0xbf7e3f7c,0xbdfbbe2f,0x3d97beb8,0x3f7fbf6f,0xbf423f6a,0xbf273ecf,0xbedb3f18,0xbf673f4e,0x3f67bf4e,0xbedb3f18,
0xbd493e79,0xbf803f78,0x3f80bf78,0xbd493e79,0x3eacbe16,0xbf713f7d,0x3f71bf7d,0x3eacbe16,0x3f2cbf04,0xbf3e3f5c,0x3f3ebf5c,0x3f2cbf04,
0xbf513f42,0x3f13bf27,0xbf7c3f7f,0xbe2f3d97,0xbf6a3f5f,0x3ecfbefc,0xbf6f3f77,0xbeb83e89,0xbf7a3f73,0x3e60bea1,0xbf583f65,0xbf093ee6,
0xbf803f7e,0x3cc9bdfb,0xbf393f4a,0xbf313f1d,0x3f803f80,0xbf353f35,0x3f803f80,0xbf353f35,0x3f803f80,0xbf353f35,0x3f803f80,0xbf353f35,
0x3f803f80,0xbf353f35,0x3f803f80,0xbf353f35,0x3f803f80,0xbf353f35,0x3f803f80,0xbf353f35,0xbf7cbf7f,0x3e2f3d97,0xbf13bf27,0x3f513f42,
0xbf6fbf77,0x3eb83e89,0xbecfbefc,0x3f6a3f5f,0xbf58bf65,0x3f093ee6,0xbe60bea1,0x3f7a3f73,0xbf39bf4a,0x3f313f1d,0xbcc9bdfb,0x3f803f7e,
0x3f713f7d,0xbeacbe16,0xbeacbe16,0xbf71bf7d,0x3f3e3f5c,0xbf2cbf04,0xbf2cbf04,0xbf3ebf5c,0x3edb3f18,0xbf67bf4e,0xbf67bf4e,0xbedbbf18,
0x3d493e79,0xbf80bf78,0xbf80bf78,0xbd49be79,0xbf5fbf7a,0x3efc3e60,0x3f773f58,0x3e893f09,0xbee6bf31,0x3f653f39,0x3f733f80,0xbea1bcc9,
0x3dfbbe2f,0x3f7e3f7c,0x3f1d3f51,0xbf4abf13,0x3f273ecf,0x3f423f6a,0x3d973eb8,0xbf7fbf6f,0x3f463f75,0xbf22be95,0xbf46bf75,0x3f223e95,
0x3dc93ef1,0xbf7fbf62,0xbdc9bef1,0x3f7f3f62,0xbf22be95,0xbf46bf75,0x3f223e95,0x3f463f75,0xbf7fbf62,0xbdc9bef1,0x3f7f3f62,0x3dc93ef1,
0xbf27bf6f,0x3f423eb8,0xbd973ecf,0xbf7fbf6a,0x3e89be60,0x3f773f7a,0xbf5fbf09,0xbefcbf58,0x3f733f31,0x3ea13f39,0xbf65bf80,0x3ee6bcc9,
0x3f4a3f7c,0xbf1dbe2f,0xbdfbbf13,0x3f7e3f51,0x3f043f67,0xbf5cbedb,0x3f5c3edb,0x3f043f67,0xbf18bd49,0xbf4ebf80,0x3f4e3f80,0xbf18bd49,
0xbf78bf71,0x3e79beac,0xbe793eac,0xbf78bf71,0xbe16bf2c,0x3f7d3f3e,0xbf7dbf3e,0xbe16bf2c,0xbeb8bf5f,0x3f6f3efc,0xbf6abf77,0x3ecfbe89,
0x3f583ea1,0x3f093f73,0x3e60bee6,0x3f7a3f65,0x3f313f7e,0xbf39bdfb,0x3f803f4a,0xbcc93f1d,0xbf133d97,0xbf51bf7f,0x3e2f3f42,0xbf7cbf27,
0x3e483f55,0xbf7bbf0e,0x3e483f55,0xbf7bbf0e,0xbf7bbf0e,0xbe48bf55,0xbf7bbf0e,0xbe48bf55,0xbe48bf55,0x3f7b3f0e,0xbe48bf55,0x3f7b3f0e,
0x3f7b3f0e,0x3e483f55,0x3f7b3f0e,0x3e483f55,0xbcc9bf4a,0x3f803f1d,0x3f31bdfb,0x3f393f7e,0x3f7c3f42,0xbe2f3f27,0x3f133f7f,0xbf51bd97,
0xbeb83efc,0xbf6fbf5f,0xbf6abe89,0xbecfbf77,0xbf58bf73,0x3f09bea1,0xbe60bf65,0x3f7a3ee6,0xbe163f3e,0xbf7dbf2c,0xbf7dbf2c,0x3e16bf3e,
0xbf5cbf67,0x3f04bedb,0x3f04bedb,0x3f5c3f67,0x3f4ebd49,0x3f183f80,0x3f183f80,0xbf4e3d49,0x3e793f71,0xbf78beac,0xbf78beac,0xbe79bf71,
0x3ea1bf31,0x3f733f39,0x3ee63f80,0xbf65bcc9,0x3f1d3f7c,0xbf4a3e2f,0xbf7ebf13,0x3dfbbf51,0xbf7fbecf,0xbd97bf6a,0x3f27beb8,0x3f423f6f,
0x3efcbf09,0x3f5f3f58,0x3e893f7a,0xbf77be60,0xbef13f22,0xbf62bf46,0x3ef1bf22,0x3f623f46,0xbe95bf7f,0x3f753dc9,0x3e953f7f,0xbf75bdc9,
0x3f623f46,0xbef13f22,0xbf62bf46,0x3ef1bf22,0xbf75bdc9,0xbe95bf7f,0x3f753dc9,0x3e953f7f,0x3f1dbf13,0x3f4a3f51,0xbf7ebe2f,0xbdfbbf7c,
0xbd973f6f,0xbf7fbeb8,0x3f42becf,0x3f273f6a,0xbefcbf7a,0x3f5fbe60,0xbe893f58,0xbf77bf09,0x3f653f31,0xbee63f39,0xbea1bf80,0x3f73bcc9,
0xbf3e3f04,0xbf2cbf5c,0x3f2c3f5c,0xbf3e3f04,0x3edbbf4e,0x3f673f18,0xbf67bf18,0x3edbbf4e,0xbd493f78,0xbf80be79,0x3f803e79,0xbd493f78,
0xbeacbf7d,0x3f71be16,0xbf713e16,0xbeacbf7d,0x3f58bee6,0x3f093f65,0x3e60bf73,0x3f7a3ea1,0xbf393f1d,0xbf31bf4a,0xbcc93f7e,0xbf80bdfb,
0x3f13bf42,0x3f513f27,0xbe2fbf7f,0x3f7cbd97,0xbecf3f5f,0xbf6abefc,0x3eb83f77,0xbf6f3e89,0xbf6d3ec4,0xbec4bf6d,0xbf6d3ec4,0xbec4bf6d,
0x3f6dbec4,0x3ec43f6d,0x3f6dbec4,0x3ec43f6d,0xbf6d3ec4,0xbec4bf6d,0xbf6d3ec4,0xbec4bf6d,0x3f6dbec4,0x3ec43f6d,0x3f6dbec4,0x3ec43f6d,
0x3f7abea1,0x3e603f73,0x3f583ee6,0xbf093f65,0xbf803dfb,0xbcc9bf7e,0xbf39bf1d,0x3f31bf4a,0x3f7c3d97,0xbe2f3f7f,0x3f133f42,0xbf513f27,
0xbf6fbe89,0x3eb8bf77,0xbecfbf5f,0x3f6abefc,0xbf803e79,0xbd49bf78,0xbd49bf78,0x3f80be79,0x3f713e16,0xbeac3f7d,0xbeac3f7d,0xbf71be16,
0xbf3ebf04,0x3f2cbf5c,0x3f2cbf5c,0x3f3e3f04,0x3edb3f4e,0xbf673f18,0xbf673f18,0xbedbbf4e,0x3f7ebe2f,0xbdfb3f7c,0xbf4a3f51,0xbf1dbf13,
0xbf42becf,0x3f27bf6a,0x3f7fbeb8,0x3d973f6f,0x3e893f58,0xbf773f09,0xbf5fbe60,0x3efcbf7a,0x3ea1bf80,0x3f733cc9,0x3ee63f39,0xbf653f31,
0xbf753dc9,0x3e95bf7f,0x3f75bdc9,0xbe953f7f,0x3ef13f22,0xbf623f46,0xbef1bf22,0x3f62bf46,0x3e95bf7f,0x3f75bdc9,0xbe953f7f,0xbf753dc9,
0xbf623f46,0xbef1bf22,0x3f62bf46,0x3ef13f22,0x3f65bcc9,0xbee63f80,0xbea1bf31,0x3f73bf39,0xbdfbbf51,0x3f7ebf13,0xbf1d3f7c,0xbf4abe2f,
0xbf423f6f,0xbf27beb8,0x3f7fbecf,0xbd973f6a,0x3f77be60,0xbe893f7a,0xbefcbf09,0x3f5fbf58,0xbf4ebd49,0x3f18bf80,0xbf183f80,0xbf4ebd49,
0xbe793f71,0xbf783eac,0x3f78beac,0xbe793f71,0x3f7dbf2c,0x3e163f3e,0xbe16bf3e,0x3f7dbf2c,0xbf04bedb,0x3f5cbf67,0xbf5c3f67,0xbf04bedb,
0x3f313dfb,0xbf393f7e,0x3f80bf1d,0xbcc93f4a,0x3f13bf7f,0x3f51bd97,0xbe2fbf27,0x3f7cbf42,0xbf6a3e89,0x3ecfbf77,0xbf6f3f5f,0xbeb8befc,
0xbe603f65,0xbf7a3ee6,0x3f093ea1,0xbf583f73,0xbf0ebe48,0x3f55bf7b,0xbf0ebe48,0x3f55bf7b,0xbf553f7b,0xbf0ebe48,0xbf553f7b,0xbf0ebe48,
0x3f0e3e48,0xbf553f7b,0x3f0e3e48,0xbf553f7b,0x3f55bf7b,0x3f0e3e48,0x3f55bf7b,0x3f0e3e48,0x3ecf3e89,0xbf6a3f77,0xbeb83f5f,0xbf6f3efc,
0x3f7abf65,0x3e603ee6,0x3f58bea1,0xbf093f73,0xbcc9bf1d,0x3f80bf4a,0x3f31bf7e,0x3f39bdfb,0xbf7c3f27,0x3e2fbf42,0xbf13bd97,0x3f51bf7f,
0xbe79beac,0x3f78bf71,0x3f78bf71,0x3e793eac,0xbf7d3f3e,0x3e16bf2c,0x3e16bf2c,0x3f7dbf3e,0xbf043f67,0xbf5c3edb,0xbf5c3edb,0x3f04bf67,
0x3f18bd49,0xbf4e3f80,0xbf4e3f80,0xbf183d49,0x3d973ecf,0xbf7f3f6a,0xbf423eb8,0x3f27bf6f,0x3f5fbf09,0xbefc3f58,0xbf773f7a,0xbe89be60,
0x3f65bf80,0x3ee63cc9,0xbea13f39,0xbf733f31,0x3dfbbf13,0x3f7ebf51,0x3f1dbe2f,0xbf4a3f7c,0x3dc9bef1,0x3f7fbf62,0xbdc93ef1,0xbf7f3f62,
0xbf223e95,0x3f46bf75,0x3f22be95,0xbf463f75,0xbf7f3f62,0x3dc9bef1,0x3f7fbf62,0xbdc93ef1,0xbf463f75,0xbf223e95,0x3f46bf75,0x3f22be95,
0xbe893f09,0xbf773f58,0x3f5fbf7a,0x3efcbe60,0x3ea1bcc9,0xbf733f80,0x3ee6bf31,0x3f65bf39,0x3f4abf13,0xbf1d3f51,0xbdfbbe2f,0x3f7ebf7c,
0x3f7fbf6f,0xbd973eb8,0xbf273ecf,0x3f42bf6a,0x3edbbf18,0x3f67bf4e,0xbf673f4e,0x3edbbf18,0x3d49be79,0x3f80bf78,0xbf803f78,0x3d49be79,
0xbeac3e16,0x3f71bf7d,0xbf713f7d,0xbeac3e16,0xbf2c3f04,0x3f3ebf5c,0xbf3e3f5c,0xbf2c3f04,0xbf133f27,0xbf513f42,0x3e2fbd97,0xbf7c3f7f,
0xbecf3efc,0xbf6a3f5f,0x3eb8be89,0xbf6f3f77,0xbe603ea1,0xbf7a3f73,0x3f09bee6,0xbf583f65,0xbcc93dfb,0xbf803f7e,0x3f31bf1d,0xbf393f4a,
0x3f803f80,0xbf353f35,0x3f803f80,0xbf353f35,0x3f803f80,0xbf353f35,0x3f803f80,0xbf353f35,0x3f803f80,0xbf353f35,0x3f803f80,0xbf353f35,
0x3f803f80,0xbf353f35,0x3f803f80,0xbf353f35,0x3e2f3d97,0x3f7c3f7f,0x3f513f42,0x3f133f27,0x3eb83e89,0x3f6f3f77,0x3f6a3f5f,0x3ecf3efc,
0x3f093ee6,0x3f583f65,0x3f7a3f73,0x3e603ea1,0x3f313f1d,0x3f393f4a,0x3f803f7e,0x3cc93dfb,0xbf71bf7d,0x3eac3e16,0x3eac3e16,0x3f713f7d,
0xbf3ebf5c,0x3f2c3f04,0x3f2c3f04,0x3f3e3f5c,0xbedbbf18,0x3f673f4e,0x3f673f4e,0x3edb3f18,0xbd49be79,0x3f803f78,0x3f803f78,0x3d493e79,
0xbefcbe60,0xbf5fbf7a,0xbe89bf09,0x3f773f58,0xbf65bf39,0xbee6bf31,0x3ea13cc9,0x3f733f80,0xbf7ebf7c,0x3dfbbe2f,0x3f4a3f13,0x3f1d3f51,
0xbf42bf6a,0x3f273ecf,0x3f7f3f6f,0x3d973eb8,0x3f463f75,0xbf22be95,0xbf46bf75,0x3f223e95,0x3dc93ef1,0xbf7fbf62,0xbdc9bef1,0x3f7f3f62,
0xbf22be95,0xbf46bf75,0x3f223e95,0x3f463f75,0xbf7fbf62,0xbdc9bef1,0x3f7f3f62,0x3dc93ef1,0x3f423eb8,0x3f273f6f,0xbf7fbf6a,0x3d97becf,
0x3f773f7a,0xbe893e60,0xbefcbf58,0x3f5f3f09,0x3ea13f39,0xbf73bf31,0x3ee6bcc9,0x3f653f80,0xbf1dbe2f,0xbf4abf7c,0x3f7e3f51,0x3dfb3f13,
0xbf04bf67,0x3f5c3edb,0xbf5cbedb,0xbf04bf67,0x3f183d49,0x3f4e3f80,0xbf4ebf80,0x3f183d49,0x3f783f71,0xbe793eac,0x3e79beac,0x3f783f71,
0x3e163f2c,0xbf7dbf3e,0x3f7d3f3e,0x3e163f2c,0xbf6fbefc,0xbeb8bf5f,0xbecf3e89,0xbf6abf77,0xbf09bf73,0x3f583ea1,0xbf7abf65,0x3e60bee6,
0x3f393dfb,0x3f313f7e,0x3cc9bf1d,0x3f803f4a,0x3f513f7f,0xbf133d97,0x3f7c3f27,0x3e2f3f42,0x3e483f55,0xbf7bbf0e,0x3e483f55,0xbf7bbf0e,
0xbf7bbf0e,0xbe48bf55,0xbf7bbf0e,0xbe48bf55,0xbe48bf55,0x3f7b3f0e,0xbe48bf55,0x3f7b3f0e,0x3f7b3f0e,0x3e483f55,0x3f7b3f0e,0x3e483f55,
0x3f803f1d,0x3cc93f4a,0x3f393f7e,0xbf313dfb,0xbe2f3f27,0xbf7cbf42,0xbf51bd97,0xbf13bf7f,0xbf6fbf5f,0x3eb8befc,0xbecfbf77,0x3f6a3e89,
0x3f09bea1,0x3f583f73,0x3f7a3ee6,0x3e603f65,0x3e16bf3e,0x3f7d3f2c,0x3f7d3f2c,0xbe163f3e,0x3f5c3f67,0xbf043edb,0xbf043edb,0xbf5cbf67,
0xbf4e3d49,0xbf18bf80,0xbf18bf80,0x3f4ebd49,0xbe79bf71,0x3f783eac,0x3f783eac,0x3e793f71,0xbf73bf39,0x3ea1bf31,0x3f653cc9,0x3ee63f80,
0x3f4abe2f,0x3f1d3f7c,0xbdfb3f51,0xbf7ebf13,0x3d973f6a,0xbf7fbecf,0xbf42bf6f,0x3f27beb8,0xbf5fbf58,0x3efcbf09,0x3f773e60,0x3e893f7a,
0xbef13f22,0xbf62bf46,0x3ef1bf22,0x3f623f46,0xbe95bf7f,0x3f753dc9,0x3e953f7f,0xbf75bdc9,0x3f623f46,0xbef13f22,0xbf62bf46,0x3ef1bf22,
0xbf75bdc9,0xbe95bf7f,0x3f753dc9,0x3e953f7f,0x3f4a3f51,0xbf1d3f13,0xbdfbbf7c,0x3f7e3e2f,0xbf7fbeb8,0x3d97bf6f,0x3f273f6a,0xbf423ecf,
0x3f5fbe60,0x3efc3f7a,0xbf77bf09,0x3e89bf58,0xbee63f39,0xbf65bf31,0x3f73bcc9,0x3ea13f80,0x3f3ebf04,0x3f2c3f5c,0xbf2cbf5c,0x3f3ebf04,
0xbedb3f4e,0xbf67bf18,0x3f673f18,0xbedb3f4e,0x3d49bf78,0x3f803e79,0xbf80be79,0x3d49bf78,0x3eac3f7d,0xbf713e16,0x3f71be16,0x3eac3f7d,
0xbf09bf65,0x3f58bee6,0xbf7abea1,0x3e60bf73,0x3f313f4a,0xbf393f1d,0x3f803dfb,0xbcc93f7e,0xbf51bf27,0x3f13bf42,0xbf7c3d97,0xbe2fbf7f,
0x3f6a3efc,0xbecf3f5f,0x3f6fbe89,0x3eb83f77,0xbf6d3ec4,0xbec4bf6d,0xbf6d3ec4,0xbec4bf6d,0x3f6dbec4,0x3ec43f6d,0x3f6dbec4,0x3ec43f6d,
0xbf6d3ec4,0xbec4bf6d,0xbf6d3ec4,0xbec4bf6d,0x3f6dbec4,0x3ec43f6d,0x3f6dbec4,0x3ec43f6d,0x3e603f73,0xbf7a3ea1,0xbf093f65,0xbf58bee6,
0xbcc9bf7e,0x3f80bdfb,0x3f31bf4a,0x3f393f1d,0xbe2f3f7f,0xbf7cbd97,0xbf513f27,0xbf13bf42,0x3eb8bf77,0x3f6f3e89,0x3f6abefc,0x3ecf3f5f,
0x3f80be79,0x3d493f78,0x3d493f78,0xbf803e79,0xbf71be16,0x3eacbf7d,0x3eacbf7d,0x3f713e16,0x3f3e3f04,0xbf2c3f5c,0xbf2c3f5c,0xbf3ebf04,
0xbedbbf4e,0x3f67bf18,0x3f67bf18,0x3edb3f4e,0x3dfbbf7c,0x3f7ebe2f,0x3f1d3f13,0xbf4a3f51,0xbf273f6a,0xbf42becf,0xbd97bf6f,0x3f7fbeb8,
0x3f77bf09,0x3e893f58,0xbefc3f7a,0xbf5fbe60,0xbf73bcc9,0x3ea1bf80,0x3f65bf31,0x3ee63f39,0xbf753dc9,0x3e95bf7f,0x3f75bdc9,0xbe953f7f,
0x3ef13f22,0xbf623f46,0xbef1bf22,0x3f62bf46,0x3e95bf7f,0x3f75bdc9,0xbe953f7f,0xbf753dc9,0xbf623f46,0xbef1bf22,0x3f62bf46,0x3ef13f22,
0xbee63f80,0xbf653cc9,0x3f73bf39,0x3ea13f31,0x3f7ebf13,0x3dfb3f51,0xbf4abe2f,0x3f1dbf7c,0xbf27beb8,0x3f42bf6f,0xbd973f6a,0xbf7f3ecf,
0xbe893f7a,0xbf773e60,0x3f5fbf58,0x3efc3f09,0x3f4e3d49,0xbf183f80,0x3f18bf80,0x3f4e3d49,0x3e79bf71,0x3f78beac,0xbf783eac,0x3e79bf71,
0xbf7d3f2c,0xbe16bf3e,0x3e163f3e,0xbf7d3f2c,0x3f043edb,0xbf5c3f67,0x3f5cbf67,0x3f043edb,0x3f39bf7e,0x3f313dfb,0x3cc9bf4a,0x3f80bf1d,
0xbf513d97,0x3f13bf7f,0xbf7c3f42,0xbe2fbf27,0xbecf3f77,0xbf6a3e89,0x3eb83efc,0xbf6f3f5f,0x3f7abee6,0xbe603f65,0x3f58bf73,0x3f093ea1,
0xbf0ebe48,0x3f55bf7b,0xbf0ebe48,0x3f55bf7b,0xbf553f7b,0xbf0ebe48,0xbf553f7b,0xbf0ebe48,0x3f0e3e48,0xbf553f7b,0x3f0e3e48,0xbf553f7b,
0x3f55bf7b,0x3f0e3e48,0x3f55bf7b,0x3f0e3e48,0xbf6a3f77,0xbecfbe89,0xbf6f3efc,0x3eb8bf5f,0x3e603ee6,0xbf7a3f65,0xbf093f73,0xbf583ea1,
0x3f80bf4a,0x3cc93f1d,0x3f39bdfb,0xbf313f7e,0x3e2fbf42,0x3f7cbf27,0x3f51bf7f,0x3f133d97,0x3e793eac,0xbf783f71,0xbf783f71,0xbe79beac,
0x3f7dbf3e,0xbe163f2c,0xbe163f2c,0xbf7d3f3e,0x3f04bf67,0x3f5cbedb,0x3f5cbedb,0xbf043f67,0xbf183d49,0x3f4ebf80,0x3f4ebf80,0x3f18bd49,
0x3f7fbf6a,0x3d973ecf,0xbf273f6f,0xbf423eb8,0x3efcbf58,0x3f5fbf09,0x3e893e60,0xbf773f7a,0xbee6bcc9,0x3f65bf80,0x3f73bf31,0xbea13f39,
0xbf7e3f51,0x3dfbbf13,0x3f4abf7c,0x3f1dbe2f,0x3dc9bef1,0x3f7fbf62,0xbdc93ef1,0xbf7f3f62,0xbf223e95,0x3f46bf75,0x3f22be95,0xbf463f75,
0xbf7f3f62,0x3dc9bef1,0x3f7fbf62,0xbdc93ef1,0xbf463f75,0xbf223e95,0x3f46bf75,0x3f22be95,0xbf773f58,0x3e89bf09,0x3efcbe60,0xbf5f3f7a,
0xbf733f80,0xbea13cc9,0x3f65bf39,0xbee63f31,0xbf1d3f51,0xbf4a3f13,0x3f7ebf7c,0x3dfb3e2f,0xbd973eb8,0xbf7f3f6f,0x3f42bf6a,0x3f27becf,
0xbedb3f18,0xbf673f4e,0x3f67bf4e,0xbedb3f18,0xbd493e79,0xbf803f78,0x3f80bf78,0xbd493e79,0x3eacbe16,0xbf713f7d,0x3f71bf7d,0x3eacbe16,
0x3f2cbf04,0xbf3e3f5c,0x3f3ebf5c,0x3f2cbf04,0x3f51bf42,0xbf133f27,0x3f7cbf7f,0x3e2fbd97,0x3f6abf5f,0xbecf3efc,0x3f6fbf77,0x3eb8be89,
0x3f7abf73,0xbe603ea1,0x3f58bf65,0x3f09bee6,0x3f80bf7e,0xbcc93dfb,0x3f39bf4a,0x3f31bf1d,0x3f803f80,0x3f803f80,0x3f803f80,0x3f803f80,
0x3f803f80,0x3f803f80,0x3f803f80,0x3f803f80,0x3f803f80,0x3f803f80,0x3f803f80,0x3f803f80,0x3f803f80,0x3f803f80,0x3f803f80,0x3f803f80,
0x0,0x0,0x0,0x0,0x0,0x0,0x0,0x0,0x0,0x0,0x0,0x0,
0x0,0x0,0x0,0x0,0xbe480000,0xbf0ebec4,0xbf55bf35,0xbf7bbf6d,0x3f7b3f80,0x3f553f6d,0x3f0e3f35,0x3e483ec4,
0x3e480000,0x3f0e3ec4,0x3f553f35,0x3f7b3f6d,0xbf7bbf80,0xbf55bf6d,0xbf0ebf35,0xbe48bec4,0x3f7b3f80,0x3f553f6d,0x3f0e3f35,0x3e483ec4,
0x3e480000,0x3f0e3ec4,0x3f553f35,0x3f7b3f6d,0xbf7bbf80,0xbf55bf6d,0xbf0ebf35,0xbe48bec4,0xbe480000,0xbf0ebec4,0xbf55bf35,0xbf7bbf6d,
0x3f6d3f80,0x3ec43f35,0xbec40000,0xbf6dbf35,0xbf6dbf80,0xbec4bf35,0x3ec40000,0x3f6d3f35,0x3f6d3f80,0x3ec43f35,0xbec40000,0xbf6dbf35,
0xbf6dbf80,0xbec4bf35,0x3ec40000,0x3f6d3f35,0x3ec40000,0x3f6d3f35,0x3f6d3f80,0x3ec43f35,0xbec40000,0xbf6dbf35,0xbf6dbf80,0xbec4bf35,
0x3ec40000,0x3f6d3f35,0x3f6d3f80,0x3ec43f35,0xbec40000,0xbf6dbf35,0xbf6dbf80,0xbec4bf35,0xbf0e0000,0xbf7bbf6d,0xbe48bf35,0x3f553ec4,
0xbf55bf80,0x3e48bec4,0x3f7b3f35,0x3f0e3f6d,0x3f0e0000,0x3f7b3f6d,0x3e483f35,0xbf55bec4,0x3f553f80,0xbe483ec4,0xbf7bbf35,0xbf0ebf6d,
0x3f553f80,0xbe483ec4,0xbf7bbf35,0xbf0ebf6d,0xbf0e0000,0xbf7bbf6d,0xbe48bf35,0x3f553ec4,0xbf55bf80,0x3e48bec4,0x3f7b3f35,0x3f0e3f6d,
0x3f0e0000,0x3f7b3f6d,0x3e483f35,0xbf55bec4,0x3f350000,0x3f353f80,0xbf350000,0xbf35bf80,0x3f350000,0x3f353f80,0xbf350000,0xbf35bf80,
0x3f350000,0x3f353f80,0xbf350000,0xbf35bf80,0x3f350000,0x3f353f80,0xbf350000,0xbf35bf80,0x3f353f80,0xbf350000,0xbf35bf80,0x3f350000,
0x3f353f80,0xbf350000,0xbf35bf80,0x3f350000,0x3f353f80,0xbf350000,0xbf35bf80,0x3f350000,0x3f353f80,0xbf350000,0xbf35bf80,0x3f350000,
0x3f0e3f80,0xbf7bbec4,0x3e48bf35,0x3f553f6d,0x3f550000,0x3e483f6d,0xbf7bbf35,0x3f0ebec4,0xbf0ebf80,0x3f7b3ec4,0xbe483f35,0xbf55bf6d,
0xbf550000,0xbe48bf6d,0x3f7b3f35,0xbf0e3ec4,0xbf550000,0xbe48bf6d,0x3f7b3f35,0xbf0e3ec4,0x3f0e3f80,0xbf7bbec4,0x3e48bf35,0x3f553f6d,
0x3f550000,0x3e483f6d,0xbf7bbf35,0x3f0ebec4,0xbf0ebf80,0x3f7b3ec4,0xbe483f35,0xbf55bf6d,0x3f6d0000,0xbec43f35,0xbec4bf80,0x3f6d3f35,
0xbf6d0000,0x3ec4bf35,0x3ec43f80,0xbf6dbf35,0x3f6d0000,0xbec43f35,0xbec4bf80,0x3f6d3f35,0xbf6d0000,0x3ec4bf35,0x3ec43f80,0xbf6dbf35,
0x3ec43f80,0xbf6dbf35,0x3f6d0000,0xbec43f35,0xbec4bf80,0x3f6d3f35,0xbf6d0000,0x3ec4bf35,0x3ec43f80,0xbf6dbf35,0x3f6d0000,0xbec43f35,
0xbec4bf80,0x3f6d3f35,0xbf6d0000,0x3ec4bf35,0x3e483f80,0xbf0ebf6d,0x3f553f35,0xbf7bbec4,0xbf7b0000,0x3f55bec4,0xbf0e3f35,0x3e48bf6d,
0xbe48bf80,0x3f0e3f6d,0xbf55bf35,0x3f7b3ec4,0x3f7b0000,0xbf553ec4,0x3f0ebf35,0xbe483f6d,0xbf7b0000,0x3f55bec4,0xbf0e3f35,0x3e48bf6d,
0xbe48bf80,0x3f0e3f6d,0xbf55bf35,0x3f7b3ec4,0x3f7b0000,0xbf553ec4,0x3f0ebf35,0xbe483f6d,0x3e483f80,0xbf0ebf6d,0x3f553f35,0xbf7bbec4,
0x3f80,0xbf80,0x3f80,0xbf80,0x3f80,0xbf80,0x3f80,0xbf80,0x3f80,0xbf80,0x3f80,0xbf80,
0x3f80,0xbf80,0x3f80,0xbf80,0x3f800000,0xbf800000,0x3f800000,0xbf800000,0x3f800000,0xbf800000,0x3f800000,0xbf800000,
0x3f800000,0xbf800000,0x3f800000,0xbf800000,0x3f800000,0xbf800000,0x3f800000,0xbf800000,0xbf7b0000,0x3f553ec4,0xbf0ebf35,0x3e483f6d,
0xbe483f80,0x3f0ebf6d,0xbf553f35,0x3f7bbec4,0x3f7b0000,0xbf55bec4,0x3f0e3f35,0xbe48bf6d,0x3e48bf80,0xbf0e3f6d,0x3f55bf35,0xbf7b3ec4,
0xbe483f80,0x3f0ebf6d,0xbf553f35,0x3f7bbec4,0x3f7b0000,0xbf55bec4,0x3f0e3f35,0xbe48bf6d,0x3e48bf80,0xbf0e3f6d,0x3f55bf35,0xbf7b3ec4,
0xbf7b0000,0x3f553ec4,0xbf0ebf35,0x3e483f6d,0xbec43f80,0x3f6dbf35,0xbf6d0000,0x3ec43f35,0x3ec4bf80,0xbf6d3f35,0x3f6d0000,0xbec4bf35,
0xbec43f80,0x3f6dbf35,0xbf6d0000,0x3ec43f35,0x3ec4bf80,0xbf6d3f35,0x3f6d0000,0xbec4bf35,0x3f6d0000,0xbec4bf35,0xbec43f80,0x3f6dbf35,
0xbf6d0000,0x3ec43f35,0x3ec4bf80,0xbf6d3f35,0x3f6d0000,0xbec4bf35,0xbec43f80,0x3f6dbf35,0xbf6d0000,0x3ec43f35,0x3ec4bf80,0xbf6d3f35,
0xbf550000,0xbe483f6d,0x3f7bbf35,0xbf0ebec4,0x3f0ebf80,0xbf7b3ec4,0x3e483f35,0x3f55bf6d,0x3f550000,0x3e48bf6d,0xbf7b3f35,0x3f0e3ec4,
0xbf0e3f80,0x3f7bbec4,0xbe48bf35,0xbf553f6d,0xbf0e3f80,0x3f7bbec4,0xbe48bf35,0xbf553f6d,0xbf550000,0xbe483f6d,0x3f7bbf35,0xbf0ebec4,
0x3f0ebf80,0xbf7b3ec4,0x3e483f35,0x3f55bf6d,0x3f550000,0x3e48bf6d,0xbf7b3f35,0x3f0e3ec4,0x3f350000,0x3f35bf80,0xbf350000,0xbf353f80,
0x3f350000,0x3f35bf80,0xbf350000,0xbf353f80,0x3f350000,0x3f35bf80,0xbf350000,0xbf353f80,0x3f350000,0x3f35bf80,0xbf350000,0xbf353f80,
0xbf353f80,0x3f350000,0x3f35bf80,0xbf350000,0xbf353f80,0x3f350000,0x3f35bf80,0xbf350000,0xbf353f80,0x3f350000,0x3f35bf80,0xbf350000,
0xbf353f80,0x3f350000,0x3f35bf80,0xbf350000,0xbf553f80,0x3e483ec4,0x3f7bbf35,0x3f0ebf6d,0x3f0e0000,0x3f7bbf6d,0x3e48bf35,0xbf553ec4,
0x3f55bf80,0xbe48bec4,0xbf7b3f35,0xbf0e3f6d,0xbf0e0000,0xbf7b3f6d,0xbe483f35,0x3f55bec4,0xbf0e0000,0xbf7b3f6d,0xbe483f35,0x3f55bec4,
0xbf553f80,0x3e483ec4,0x3f7bbf35,0x3f0ebf6d,0x3f0e0000,0x3f7bbf6d,0x3e48bf35,0xbf553ec4,0x3f55bf80,0xbe48bec4,0xbf7b3f35,0xbf0e3f6d,
0x3ec40000,0x3f6dbf35,0x3f6dbf80,0x3ec4bf35,0xbec40000,0xbf6d3f35,0xbf6d3f80,0xbec43f35,0x3ec40000,0x3f6dbf35,0x3f6dbf80,0x3ec4bf35,
0xbec40000,0xbf6d3f35,0xbf6d3f80,0xbec43f35,0xbf6d3f80,0xbec43f35,0x3ec40000,0x3f6dbf35,0x3f6dbf80,0x3ec4bf35,0xbec40000,0xbf6d3f35,
0xbf6d3f80,0xbec43f35,0x3ec40000,0x3f6dbf35,0x3f6dbf80,0x3ec4bf35,0xbec40000,0xbf6d3f35,0xbf7b3f80,0xbf553f6d,0xbf0e3f35,0xbe483ec4,
0xbe480000,0xbf0e3ec4,0xbf553f35,0xbf7b3f6d,0x3f7bbf80,0x3f55bf6d,0x3f0ebf35,0x3e48bec4,0x3e480000,0x3f0ebec4,0x3f55bf35,0x3f7bbf6d,
0xbe480000,0xbf0e3ec4,0xbf553f35,0xbf7b3f6d,0x3f7bbf80,0x3f55bf6d,0x3f0ebf35,0x3e48bec4,0x3e480000,0x3f0ebec4,0x3f55bf35,0x3f7bbf6d,
0xbf7b3f80,0xbf553f6d,0xbf0e3f35,0xbe483ec4,0xbf803f80,0xbf803f80,0xbf803f80,0xbf803f80,0xbf803f80,0xbf803f80,0xbf803f80,0xbf803f80,
0xbf803f80,0xbf803f80,0xbf803f80,0xbf803f80,0xbf803f80,0xbf803f80,0xbf803f80,0xbf803f80,0x0,0x0,0x0,0x0,
0x0,0x0,0x0,0x0,0x0,0x0,0x0,0x0,0x0,0x0,0x0,0x0,
0x3e480000,0x3f0ebec4,0x3f55bf35,0x3f7bbf6d,0xbf7b3f80,0xbf553f6d,0xbf0e3f35,0xbe483ec4,0xbe480000,0xbf0e3ec4,0xbf553f35,0xbf7b3f6d,
0x3f7bbf80,0x3f55bf6d,0x3f0ebf35,0x3e48bec4,0xbf7b3f80,0xbf553f6d,0xbf0e3f35,0xbe483ec4,0xbe480000,0xbf0e3ec4,0xbf553f35,0xbf7b3f6d,
0x3f7bbf80,0x3f55bf6d,0x3f0ebf35,0x3e48bec4,0x3e480000,0x3f0ebec4,0x3f55bf35,0x3f7bbf6d,0xbf6d3f80,0xbec43f35,0x3ec40000,0x3f6dbf35,
0x3f6dbf80,0x3ec4bf35,0xbec40000,0xbf6d3f35,0xbf6d3f80,0xbec43f35,0x3ec40000,0x3f6dbf35,0x3f6dbf80,0x3ec4bf35,0xbec40000,0xbf6d3f35,
0xbec40000,0xbf6d3f35,0xbf6d3f80,0xbec43f35,0x3ec40000,0x3f6dbf35,0x3f6dbf80,0x3ec4bf35,0xbec40000,0xbf6d3f35,0xbf6d3f80,0xbec43f35,
0x3ec40000,0x3f6dbf35,0x3f6dbf80,0x3ec4bf35,0x3f0e0000,0x3f7bbf6d,0x3e48bf35,0xbf553ec4,0x3f55bf80,0xbe48bec4,0xbf7b3f35,0xbf0e3f6d,
0xbf0e0000,0xbf7b3f6d,0xbe483f35,0x3f55bec4,0xbf553f80,0x3e483ec4,0x3f7bbf35,0x3f0ebf6d,0xbf553f80,0x3e483ec4,0x3f7bbf35,0x3f0ebf6d,
0x3f0e0000,0x3f7bbf6d,0x3e48bf35,0xbf553ec4,0x3f55bf80,0xbe48bec4,0xbf7b3f35,0xbf0e3f6d,0xbf0e0000,0xbf7b3f6d,0xbe483f35,0x3f55bec4,
0xbf350000,0xbf353f80,0x3f350000,0x3f35bf80,0xbf350000,0xbf353f80,0x3f350000,0x3f35bf80,0xbf350000,0xbf353f80,0x3f350000,0x3f35bf80,
0xbf350000,0xbf353f80,0x3f350000,0x3f35bf80,0xbf353f80,0x3f350000,0x3f35bf80,0xbf350000,0xbf353f80,0x3f350000,0x3f35bf80,0xbf350000,
0xbf353f80,0x3f350000,0x3f35bf80,0xbf350000,0xbf353f80,0x3f350000,0x3f35bf80,0xbf350000,0xbf0e3f80,0x3f7bbec4,0xbe48bf35,0xbf553f6d,
0xbf550000,0xbe483f6d,0x3f7bbf35,0xbf0ebec4,0x3f0ebf80,0xbf7b3ec4,0x3e483f35,0x3f55bf6d,0x3f550000,0x3e48bf6d,0xbf7b3f35,0x3f0e3ec4,
0x3f550000,0x3e48bf6d,0xbf7b3f35,0x3f0e3ec4,0xbf0e3f80,0x3f7bbec4,0xbe48bf35,0xbf553f6d,0xbf550000,0xbe483f6d,0x3f7bbf35,0xbf0ebec4,
0x3f0ebf80,0xbf7b3ec4,0x3e483f35,0x3f55bf6d,0xbf6d0000,0x3ec43f35,0x3ec4bf80,0xbf6d3f35,0x3f6d0000,0xbec4bf35,0xbec43f80,0x3f6dbf35,
0xbf6d0000,0x3ec43f35,0x3ec4bf80,0xbf6d3f35,0x3f6d0000,0xbec4bf35,0xbec43f80,0x3f6dbf35,0xbec43f80,0x3f6dbf35,0xbf6d0000,0x3ec43f35,
0x3ec4bf80,0xbf6d3f35,0x3f6d0000,0xbec4bf35,0xbec43f80,0x3f6dbf35,0xbf6d0000,0x3ec43f35,0x3ec4bf80,0xbf6d3f35,0x3f6d0000,0xbec4bf35,
0xbe483f80,0x3f0ebf6d,0xbf553f35,0x3f7bbec4,0x3f7b0000,0xbf55bec4,0x3f0e3f35,0xbe48bf6d,0x3e48bf80,0xbf0e3f6d,0x3f55bf35,0xbf7b3ec4,
0xbf7b0000,0x3f553ec4,0xbf0ebf35,0x3e483f6d,0x3f7b0000,0xbf55bec4,0x3f0e3f35,0xbe48bf6d,0x3e48bf80,0xbf0e3f6d,0x3f55bf35,0xbf7b3ec4,
0xbf7b0000,0x3f553ec4,0xbf0ebf35,0x3e483f6d,0xbe483f80,0x3f0ebf6d,0xbf553f35,0x3f7bbec4,0x3f80,0xbf80,0x3f80,0xbf80,
0x3f80,0xbf80,0x3f80,0xbf80,0x3f80,0xbf80,0x3f80,0xbf80,0x3f80,0xbf80,0x3f80,0xbf80,
0xbf800000,0x3f800000,0xbf800000,0x3f800000,0xbf800000,0x3f800000,0xbf800000,0x3f800000,0xbf800000,0x3f800000,0xbf800000,0x3f800000,
0xbf800000,0x3f800000,0xbf800000,0x3f800000,0x3f7b0000,0xbf553ec4,0x3f0ebf35,0xbe483f6d,0x3e483f80,0xbf0ebf6d,0x3f553f35,0xbf7bbec4,
0xbf7b0000,0x3f55bec4,0xbf0e3f35,0x3e48bf6d,0xbe48bf80,0x3f0e3f6d,0xbf55bf35,0x3f7b3ec4,0x3e483f80,0xbf0ebf6d,0x3f553f35,0xbf7bbec4,
0xbf7b0000,0x3f55bec4,0xbf0e3f35,0x3e48bf6d,0xbe48bf80,0x3f0e3f6d,0xbf55bf35,0x3f7b3ec4,0x3f7b0000,0xbf553ec4,0x3f0ebf35,0xbe483f6d,
0x3ec43f80,0xbf6dbf35,0x3f6d0000,0xbec43f35,0xbec4bf80,0x3f6d3f35,0xbf6d0000,0x3ec4bf35,0x3ec43f80,0xbf6dbf35,0x3f6d0000,0xbec43f35,
0xbec4bf80,0x3f6d3f35,0xbf6d0000,0x3ec4bf35,0xbf6d0000,0x3ec4bf35,0x3ec43f80,0xbf6dbf35,0x3f6d0000,0xbec43f35,0xbec4bf80,0x3f6d3f35,
0xbf6d0000,0x3ec4bf35,0x3ec43f80,0xbf6dbf35,0x3f6d0000,0xbec43f35,0xbec4bf80,0x3f6d3f35,0x3f550000,0x3e483f6d,0xbf7bbf35,0x3f0ebec4,
0xbf0ebf80,0x3f7b3ec4,0xbe483f35,0xbf55bf6d,0xbf550000,0xbe48bf6d,0x3f7b3f35,0xbf0e3ec4,0x3f0e3f80,0xbf7bbec4,0x3e48bf35,0x3f553f6d,
0x3f0e3f80,0xbf7bbec4,0x3e48bf35,0x3f553f6d,0x3f550000,0x3e483f6d,0xbf7bbf35,0x3f0ebec4,0xbf0ebf80,0x3f7b3ec4,0xbe483f35,0xbf55bf6d,
0xbf550000,0xbe48bf6d,0x3f7b3f35,0xbf0e3ec4,0xbf350000,0xbf35bf80,0x3f350000,0x3f353f80,0xbf350000,0xbf35bf80,0x3f350000,0x3f353f80,
0xbf350000,0xbf35bf80,0x3f350000,0x3f353f80,0xbf350000,0xbf35bf80,0x3f350000,0x3f353f80,0x3f353f80,0xbf350000,0xbf35bf80,0x3f350000,
0x3f353f80,0xbf350000,0xbf35bf80,0x3f350000,0x3f353f80,0xbf350000,0xbf35bf80,0x3f350000,0x3f353f80,0xbf350000,0xbf35bf80,0x3f350000,
0x3f553f80,0xbe483ec4,0xbf7bbf35,0xbf0ebf6d,0xbf0e0000,0xbf7bbf6d,0xbe48bf35,0x3f553ec4,0xbf55bf80,0x3e48bec4,0x3f7b3f35,0x3f0e3f6d,
0x3f0e0000,0x3f7b3f6d,0x3e483f35,0xbf55bec4,0x3f0e0000,0x3f7b3f6d,0x3e483f35,0xbf55bec4,0x3f553f80,0xbe483ec4,0xbf7bbf35,0xbf0ebf6d,
0xbf0e0000,0xbf7bbf6d,0xbe48bf35,0x3f553ec4,0xbf55bf80,0x3e48bec4,0x3f7b3f35,0x3f0e3f6d,0xbec40000,0xbf6dbf35,0xbf6dbf80,0xbec4bf35,
0x3ec40000,0x3f6d3f35,0x3f6d3f80,0x3ec43f35,0xbec40000,0xbf6dbf35,0xbf6dbf80,0xbec4bf35,0x3ec40000,0x3f6d3f35,0x3f6d3f80,0x3ec43f35,
0x3f6d3f80,0x3ec43f35,0xbec40000,0xbf6dbf35,0xbf6dbf80,0xbec4bf35,0x3ec40000,0x3f6d3f35,0x3f6d3f80,0x3ec43f35,0xbec40000,0xbf6dbf35,
0xbf6dbf80,0xbec4bf35,0x3ec40000,0x3f6d3f35,0x3f7b3f80,0x3f553f6d,0x3f0e3f35,0x3e483ec4,0x3e480000,0x3f0e3ec4,0x3f553f35,0x3f7b3f6d,
0xbf7bbf80,0xbf55bf6d,0xbf0ebf35,0xbe48bec4,0xbe480000,0xbf0ebec4,0xbf55bf35,0xbf7bbf6d,0x3e480000,0x3f0e3ec4,0x3f553f35,0x3f7b3f6d,
0xbf7bbf80,0xbf55bf6d,0xbf0ebf35,0xbe48bec4,0xbe480000,0xbf0ebec4,0xbf55bf35,0xbf7bbf6d,0x3f7b3f80,0x3f553f6d,0x3f0e3f35,0x3e483ec4,
0x80008000,0x80008000,0x80008000,0x80008000,0x80008000,0x80008000,0x80008000,0x80008000,0x80008000,0x80008000,0x80008000,0x80008000,
0x80008000,0x80008000,0x80008000,0x80008000,0x3f803f80,0x3f803f80,0x3f803f80,0x3f803f80,0x3f803f80,0x3f803f80,0x3f803f80,0x3f803f80,
0x3f803f80,0x3f803f80,0x3f803f80,0x3f803f80,0x3f803f80,0x3f803f80,0x3f803f80,0x3f803f80,0xbf7bbf80,0xbf55bf6d,0xbf0ebf35,0xbe48bec4,
0xbe488000,0xbf0ebec4,0xbf55bf35,0xbf7bbf6d,0x3f7b3f80,0x3f553f6d,0x3f0e3f35,0x3e483ec4,0x3e488000,0x3f0e3ec4,0x3f553f35,0x3f7b3f6d,
0xbe480000,0xbf0ebec4,0xbf55bf35,0xbf7bbf6d,0x3f7b3f80,0x3f553f6d,0x3f0e3f35,0x3e483ec4,0x3e480000,0x3f0e3ec4,0x3f553f35,0x3f7b3f6d,
0xbf7bbf80,0xbf55bf6d,0xbf0ebf35,0xbe48bec4,0xbec48000,0xbf6dbf35,0xbf6dbf80,0xbec4bf35,0x3ec48000,0x3f6d3f35,0x3f6d3f80,0x3ec43f35,
0xbec48000,0xbf6dbf35,0xbf6dbf80,0xbec4bf35,0x3ec48000,0x3f6d3f35,0x3f6d3f80,0x3ec43f35,0x3f6d3f80,0x3ec43f35,0xbec40000,0xbf6dbf35,
0xbf6dbf80,0xbec4bf35,0x3ec40000,0x3f6d3f35,0x3f6d3f80,0x3ec43f35,0xbec40000,0xbf6dbf35,0xbf6dbf80,0xbec4bf35,0x3ec40000,0x3f6d3f35,
0xbf55bf80,0x3e48bec4,0x3f7b3f35,0x3f0e3f6d,0x3f0e8000,0x3f7b3f6d,0x3e483f35,0xbf55bec4,0x3f553f80,0xbe483ec4,0xbf7bbf35,0xbf0ebf6d,
0xbf0e8000,0xbf7bbf6d,0xbe48bf35,0x3f553ec4,0xbf0e0000,0xbf7bbf6d,0xbe48bf35,0x3f553ec4,0xbf55bf80,0x3e48bec4,0x3f7b3f35,0x3f0e3f6d,
0x3f0e0000,0x3f7b3f6d,0x3e483f35,0xbf55bec4,0x3f553f80,0xbe483ec4,0xbf7bbf35,0xbf0ebf6d,0x3f353f80,0xbf350000,0xbf35bf80,0x3f350000,
0x3f353f80,0xbf350000,0xbf35bf80,0x3f350000,0x3f353f80,0xbf350000,0xbf35bf80,0x3f350000,0x3f353f80,0xbf350000,0xbf35bf80,0x3f350000,
0xbf358000,0xbf35bf80,0x3f358000,0x3f353f80,0xbf358000,0xbf35bf80,0x3f358000,0x3f353f80,0xbf358000,0xbf35bf80,0x3f358000,0x3f353f80,
0xbf358000,0xbf35bf80,0x3f358000,0x3f353f80,0xbf550000,0xbe48bf6d,0x3f7b3f35,0xbf0e3ec4,0x3f0e3f80,0xbf7bbec4,0x3e48bf35,0x3f553f6d,
0x3f550000,0x3e483f6d,0xbf7bbf35,0x3f0ebec4,0xbf0ebf80,0x3f7b3ec4,0xbe483f35,0xbf55bf6d,0xbf0ebf80,0x3f7b3ec4,0xbe483f35,0xbf55bf6d,
0xbf558000,0xbe48bf6d,0x3f7b3f35,0xbf0e3ec4,0x3f0e3f80,0xbf7bbec4,0x3e48bf35,0x3f553f6d,0x3f558000,0x3e483f6d,0xbf7bbf35,0x3f0ebec4,
0x3ec43f80,0xbf6dbf35,0x3f6d0000,0xbec43f35,0xbec4bf80,0x3f6d3f35,0xbf6d0000,0x3ec4bf35,0x3ec43f80,0xbf6dbf35,0x3f6d0000,0xbec43f35,
0xbec4bf80,0x3f6d3f35,0xbf6d0000,0x3ec4bf35,0xbf6d8000,0x3ec4bf35,0x3ec43f80,0xbf6dbf35,0x3f6d8000,0xbec43f35,0xbec4bf80,0x3f6d3f35,
0xbf6d8000,0x3ec4bf35,0x3ec43f80,0xbf6dbf35,0x3f6d8000,0xbec43f35,0xbec4bf80,0x3f6d3f35,0xbf7b0000,0x3f55bec4,0xbf0e3f35,0x3e48bf6d,
0xbe48bf80,0x3f0e3f6d,0xbf55bf35,0x3f7b3ec4,0x3f7b0000,0xbf553ec4,0x3f0ebf35,0xbe483f6d,0x3e483f80,0xbf0ebf6d,0x3f553f35,0xbf7bbec4,
0xbe48bf80,0x3f0e3f6d,0xbf55bf35,0x3f7b3ec4,0x3f7b8000,0xbf553ec4,0x3f0ebf35,0xbe483f6d,0x3e483f80,0xbf0ebf6d,0x3f553f35,0xbf7bbec4,
0xbf7b8000,0x3f55bec4,0xbf0e3f35,0x3e48bf6d,0xbf808000,0x3f808000,0xbf808000,0x3f808000,0xbf808000,0x3f808000,0xbf808000,0x3f808000,
0xbf808000,0x3f808000,0xbf808000,0x3f808000,0xbf808000,0x3f808000,0xbf808000,0x3f808000,0x3f80,0xbf80,0x3f80,0xbf80,
0x3f80,0xbf80,0x3f80,0xbf80,0x3f80,0xbf80,0x3f80,0xbf80,0x3f80,0xbf80,0x3f80,0xbf80,
0x3e48bf80,0xbf0e3f6d,0x3f55bf35,0xbf7b3ec4,0xbf7b8000,0x3f553ec4,0xbf0ebf35,0x3e483f6d,0xbe483f80,0x3f0ebf6d,0xbf553f35,0x3f7bbec4,
0x3f7b8000,0xbf55bec4,0x3f0e3f35,0xbe48bf6d,0xbf7b0000,0x3f553ec4,0xbf0ebf35,0x3e483f6d,0xbe483f80,0x3f0ebf6d,0xbf553f35,0x3f7bbec4,
0x3f7b0000,0xbf55bec4,0x3f0e3f35,0xbe48bf6d,0x3e48bf80,0xbf0e3f6d,0x3f55bf35,0xbf7b3ec4,0xbf6d8000,0x3ec43f35,0x3ec4bf80,0xbf6d3f35,
0x3f6d8000,0xbec4bf35,0xbec43f80,0x3f6dbf35,0xbf6d8000,0x3ec43f35,0x3ec4bf80,0xbf6d3f35,0x3f6d8000,0xbec4bf35,0xbec43f80,0x3f6dbf35,
0xbec43f80,0x3f6dbf35,0xbf6d0000,0x3ec43f35,0x3ec4bf80,0xbf6d3f35,0x3f6d0000,0xbec4bf35,0xbec43f80,0x3f6dbf35,0xbf6d0000,0x3ec43f35,
0x3ec4bf80,0xbf6d3f35,0x3f6d0000,0xbec4bf35,0x3f0ebf80,0xbf7b3ec4,0x3e483f35,0x3f55bf6d,0x3f558000,0x3e48bf6d,0xbf7b3f35,0x3f0e3ec4,
0xbf0e3f80,0x3f7bbec4,0xbe48bf35,0xbf553f6d,0xbf558000,0xbe483f6d,0x3f7bbf35,0xbf0ebec4,0xbf550000,0xbe483f6d,0x3f7bbf35,0xbf0ebec4,
0x3f0ebf80,0xbf7b3ec4,0x3e483f35,0x3f55bf6d,0x3f550000,0x3e48bf6d,0xbf7b3f35,0x3f0e3ec4,0xbf0e3f80,0x3f7bbec4,0xbe48bf35,0xbf553f6d,
0xbf353f80,0x3f350000,0x3f35bf80,0xbf350000,0xbf353f80,0x3f350000,0x3f35bf80,0xbf350000,0xbf353f80,0x3f350000,0x3f35bf80,0xbf350000,
0xbf353f80,0x3f350000,0x3f35bf80,0xbf350000,0xbf358000,0xbf353f80,0x3f358000,0x3f35bf80,0xbf358000,0xbf353f80,0x3f358000,0x3f35bf80,
0xbf358000,0xbf353f80,0x3f358000,0x3f35bf80,0xbf358000,0xbf353f80,0x3f358000,0x3f35bf80,0xbf0e0000,0xbf7b3f6d,0xbe483f35,0x3f55bec4,
0xbf553f80,0x3e483ec4,0x3f7bbf35,0x3f0ebf6d,0x3f0e0000,0x3f7bbf6d,0x3e48bf35,0xbf553ec4,0x3f55bf80,0xbe48bec4,0xbf7b3f35,0xbf0e3f6d,
0x3f55bf80,0xbe48bec4,0xbf7b3f35,0xbf0e3f6d,0xbf0e8000,0xbf7b3f6d,0xbe483f35,0x3f55bec4,0xbf553f80,0x3e483ec4,0x3f7bbf35,0x3f0ebf6d,
0x3f0e8000,0x3f7bbf6d,0x3e48bf35,0xbf553ec4,0xbf6d3f80,0xbec43f35,0x3ec40000,0x3f6dbf35,0x3f6dbf80,0x3ec4bf35,0xbec40000,0xbf6d3f35,
0xbf6d3f80,0xbec43f35,0x3ec40000,0x3f6dbf35,0x3f6dbf80,0x3ec4bf35,0xbec40000,0xbf6d3f35,0xbec48000,0xbf6d3f35,0xbf6d3f80,0xbec43f35,
0x3ec48000,0x3f6dbf35,0x3f6dbf80,0x3ec4bf35,0xbec48000,0xbf6d3f35,0xbf6d3f80,0xbec43f35,0x3ec48000,0x3f6dbf35,0x3f6dbf80,0x3ec4bf35,
0xbe480000,0xbf0e3ec4,0xbf553f35,0xbf7b3f6d,0x3f7bbf80,0x3f55bf6d,0x3f0ebf35,0x3e48bec4,0x3e480000,0x3f0ebec4,0x3f55bf35,0x3f7bbf6d,
0xbf7b3f80,0xbf553f6d,0xbf0e3f35,0xbe483ec4,0x3f7bbf80,0x3f55bf6d,0x3f0ebf35,0x3e48bec4,0x3e488000,0x3f0ebec4,0x3f55bf35,0x3f7bbf6d,
0xbf7b3f80,0xbf553f6d,0xbf0e3f35,0xbe483ec4,0xbe488000,0xbf0e3ec4,0xbf553f35,0xbf7b3f6d,0x80008000,0x80008000,0x80008000,0x80008000,
0x80008000,0x80008000,0x80008000,0x80008000,0x80008000,0x80008000,0x80008000,0x80008000,0x80008000,0x80008000,0x80008000,0x80008000,
0xbf803f80,0xbf803f80,0xbf803f80,0xbf803f80,0xbf803f80,0xbf803f80,0xbf803f80,0xbf803f80,0xbf803f80,0xbf803f80,0xbf803f80,0xbf803f80,
0xbf803f80,0xbf803f80,0xbf803f80,0xbf803f80,0x3f7bbf80,0x3f55bf6d,0x3f0ebf35,0x3e48bec4,0x3e488000,0x3f0ebec4,0x3f55bf35,0x3f7bbf6d,
0xbf7b3f80,0xbf553f6d,0xbf0e3f35,0xbe483ec4,0xbe488000,0xbf0e3ec4,0xbf553f35,0xbf7b3f6d,0x3e480000,0x3f0ebec4,0x3f55bf35,0x3f7bbf6d,
0xbf7b3f80,0xbf553f6d,0xbf0e3f35,0xbe483ec4,0xbe480000,0xbf0e3ec4,0xbf553f35,0xbf7b3f6d,0x3f7bbf80,0x3f55bf6d,0x3f0ebf35,0x3e48bec4,
0x3ec48000,0x3f6dbf35,0x3f6dbf80,0x3ec4bf35,0xbec48000,0xbf6d3f35,0xbf6d3f80,0xbec43f35,0x3ec48000,0x3f6dbf35,0x3f6dbf80,0x3ec4bf35,
0xbec48000,0xbf6d3f35,0xbf6d3f80,0xbec43f35,0xbf6d3f80,0xbec43f35,0x3ec40000,0x3f6dbf35,0x3f6dbf80,0x3ec4bf35,0xbec40000,0xbf6d3f35,
0xbf6d3f80,0xbec43f35,0x3ec40000,0x3f6dbf35,0x3f6dbf80,0x3ec4bf35,0xbec40000,0xbf6d3f35,0x3f55bf80,0xbe48bec4,0xbf7b3f35,0xbf0e3f6d,
0xbf0e8000,0xbf7b3f6d,0xbe483f35,0x3f55bec4,0xbf553f80,0x3e483ec4,0x3f7bbf35,0x3f0ebf6d,0x3f0e8000,0x3f7bbf6d,0x3e48bf35,0xbf553ec4,
0x3f0e0000,0x3f7bbf6d,0x3e48bf35,0xbf553ec4,0x3f55bf80,0xbe48bec4,0xbf7b3f35,0xbf0e3f6d,0xbf0e0000,0xbf7b3f6d,0xbe483f35,0x3f55bec4,
0xbf553f80,0x3e483ec4,0x3f7bbf35,0x3f0ebf6d,0xbf353f80,0x3f350000,0x3f35bf80,0xbf350000,0xbf353f80,0x3f350000,0x3f35bf80,0xbf350000,
0xbf353f80,0x3f350000,0x3f35bf80,0xbf350000,0xbf353f80,0x3f350000,0x3f35bf80,0xbf350000,0x3f358000,0x3f35bf80,0xbf358000,0xbf353f80,
0x3f358000,0x3f35bf80,0xbf358000,0xbf353f80,0x3f358000,0x3f35bf80,0xbf358000,0xbf353f80,0x3f358000,0x3f35bf80,0xbf358000,0xbf353f80,
0x3f550000,0x3e48bf6d,0xbf7b3f35,0x3f0e3ec4,0xbf0e3f80,0x3f7bbec4,0xbe48bf35,0xbf553f6d,0xbf550000,0xbe483f6d,0x3f7bbf35,0xbf0ebec4,
0x3f0ebf80,0xbf7b3ec4,0x3e483f35,0x3f55bf6d,0x3f0ebf80,0xbf7b3ec4,0x3e483f35,0x3f55bf6d,0x3f558000,0x3e48bf6d,0xbf7b3f35,0x3f0e3ec4,
0xbf0e3f80,0x3f7bbec4,0xbe48bf35,0xbf553f6d,0xbf558000,0xbe483f6d,0x3f7bbf35,0xbf0ebec4,0xbec43f80,0x3f6dbf35,0xbf6d0000,0x3ec43f35,
0x3ec4bf80,0xbf6d3f35,0x3f6d0000,0xbec4bf35,0xbec43f80,0x3f6dbf35,0xbf6d0000,0x3ec43f35,0x3ec4bf80,0xbf6d3f35,0x3f6d0000,0xbec4bf35,
0x3f6d8000,0xbec4bf35,0xbec43f80,0x3f6dbf35,0xbf6d8000,0x3ec43f35,0x3ec4bf80,0xbf6d3f35,0x3f6d8000,0xbec4bf35,0xbec43f80,0x3f6dbf35,
0xbf6d8000,0x3ec43f35,0x3ec4bf80,0xbf6d3f35,0x3f7b0000,0xbf55bec4,0x3f0e3f35,0xbe48bf6d,0x3e48bf80,0xbf0e3f6d,0x3f55bf35,0xbf7b3ec4,
0xbf7b0000,0x3f553ec4,0xbf0ebf35,0x3e483f6d,0xbe483f80,0x3f0ebf6d,0xbf553f35,0x3f7bbec4,0x3e48bf80,0xbf0e3f6d,0x3f55bf35,0xbf7b3ec4,
0xbf7b8000,0x3f553ec4,0xbf0ebf35,0x3e483f6d,0xbe483f80,0x3f0ebf6d,0xbf553f35,0x3f7bbec4,0x3f7b8000,0xbf55bec4,0x3f0e3f35,0xbe48bf6d,
0x3f808000,0xbf808000,0x3f808000,0xbf808000,0x3f808000,0xbf808000,0x3f808000,0xbf808000,0x3f808000,0xbf808000,0x3f808000,0xbf808000,
0x3f808000,0xbf808000,0x3f808000,0xbf808000,0x3f80,0xbf80,0x3f80,0xbf80,0x3f80,0xbf80,0x3f80,0xbf80,
0x3f80,0xbf80,0x3f80,0xbf80,0x3f80,0xbf80,0x3f80,0xbf80,0xbe48bf80,0x3f0e3f6d,0xbf55bf35,0x3f7b3ec4,
0x3f7b8000,0xbf553ec4,0x3f0ebf35,0xbe483f6d,0x3e483f80,0xbf0ebf6d,0x3f553f35,0xbf7bbec4,0xbf7b8000,0x3f55bec4,0xbf0e3f35,0x3e48bf6d,
0x3f7b0000,0xbf553ec4,0x3f0ebf35,0xbe483f6d,0x3e483f80,0xbf0ebf6d,0x3f553f35,0xbf7bbec4,0xbf7b0000,0x3f55bec4,0xbf0e3f35,0x3e48bf6d,
0xbe48bf80,0x3f0e3f6d,0xbf55bf35,0x3f7b3ec4,0x3f6d8000,0xbec43f35,0xbec4bf80,0x3f6d3f35,0xbf6d8000,0x3ec4bf35,0x3ec43f80,0xbf6dbf35,
0x3f6d8000,0xbec43f35,0xbec4bf80,0x3f6d3f35,0xbf6d8000,0x3ec4bf35,0x3ec43f80,0xbf6dbf35,0x3ec43f80,0xbf6dbf35,0x3f6d0000,0xbec43f35,
0xbec4bf80,0x3f6d3f35,0xbf6d0000,0x3ec4bf35,0x3ec43f80,0xbf6dbf35,0x3f6d0000,0xbec43f35,0xbec4bf80,0x3f6d3f35,0xbf6d0000,0x3ec4bf35,
0xbf0ebf80,0x3f7b3ec4,0xbe483f35,0xbf55bf6d,0xbf558000,0xbe48bf6d,0x3f7b3f35,0xbf0e3ec4,0x3f0e3f80,0xbf7bbec4,0x3e48bf35,0x3f553f6d,
0x3f558000,0x3e483f6d,0xbf7bbf35,0x3f0ebec4,0x3f550000,0x3e483f6d,0xbf7bbf35,0x3f0ebec4,0xbf0ebf80,0x3f7b3ec4,0xbe483f35,0xbf55bf6d,
0xbf550000,0xbe48bf6d,0x3f7b3f35,0xbf0e3ec4,0x3f0e3f80,0xbf7bbec4,0x3e48bf35,0x3f553f6d,0x3f353f80,0xbf350000,0xbf35bf80,0x3f350000,
0x3f353f80,0xbf350000,0xbf35bf80,0x3f350000,0x3f353f80,0xbf350000,0xbf35bf80,0x3f350000,0x3f353f80,0xbf350000,0xbf35bf80,0x3f350000,
0x3f358000,0x3f353f80,0xbf358000,0xbf35bf80,0x3f358000,0x3f353f80,0xbf358000,0xbf35bf80,0x3f358000,0x3f353f80,0xbf358000,0xbf35bf80,
0x3f358000,0x3f353f80,0xbf358000,0xbf35bf80,0x3f0e0000,0x3f7b3f6d,0x3e483f35,0xbf55bec4,0x3f553f80,0xbe483ec4,0xbf7bbf35,0xbf0ebf6d,
0xbf0e0000,0xbf7bbf6d,0xbe48bf35,0x3f553ec4,0xbf55bf80,0x3e48bec4,0x3f7b3f35,0x3f0e3f6d,0xbf55bf80,0x3e48bec4,0x3f7b3f35,0x3f0e3f6d,
0x3f0e8000,0x3f7b3f6d,0x3e483f35,0xbf55bec4,0x3f553f80,0xbe483ec4,0xbf7bbf35,0xbf0ebf6d,0xbf0e8000,0xbf7bbf6d,0xbe48bf35,0x3f553ec4,
0x3f6d3f80,0x3ec43f35,0xbec40000,0xbf6dbf35,0xbf6dbf80,0xbec4bf35,0x3ec40000,0x3f6d3f35,0x3f6d3f80,0x3ec43f35,0xbec40000,0xbf6dbf35,
0xbf6dbf80,0xbec4bf35,0x3ec40000,0x3f6d3f35,0x3ec48000,0x3f6d3f35,0x3f6d3f80,0x3ec43f35,0xbec48000,0xbf6dbf35,0xbf6dbf80,0xbec4bf35,
0x3ec48000,0x3f6d3f35,0x3f6d3f80,0x3ec43f35,0xbec48000,0xbf6dbf35,0xbf6dbf80,0xbec4bf35,0x3e480000,0x3f0e3ec4,0x3f553f35,0x3f7b3f6d,
0xbf7bbf80,0xbf55bf6d,0xbf0ebf35,0xbe48bec4,0xbe480000,0xbf0ebec4,0xbf55bf35,0xbf7bbf6d,0x3f7b3f80,0x3f553f6d,0x3f0e3f35,0x3e483ec4,
0xbf7bbf80,0xbf55bf6d,0xbf0ebf35,0xbe48bec4,0xbe488000,0xbf0ebec4,0xbf55bf35,0xbf7bbf6d,0x3f7b3f80,0x3f553f6d,0x3f0e3f35,0x3e483ec4,
0x3e488000,0x3f0e3ec4,0x3f553f35,0x3f7b3f6d,0x3f803f80,0x80008000,0x3f803f80,0x80008000,0x3f803f80,0x80008000,0x3f803f80,0x80008000,
0x3f803f80,0x80008000,0x3f803f80,0x80008000,0x3f803f80,0x80008000,0x3f803f80,0x80008000,0x3f803f80,0xbbc98000,0x3f803f80,0xbd62bd49,
0x3f803f80,0xbc97bc49,0x3f7f3f80,0xbd8abd7b,0x3f803f80,0xbcfbbcc9,0x3f7f3f7f,0xbda3bd97,0x3f803f80,0xbd30bd17,0x3f7f3f7f,0xbdbcbdb0,
0x3f803f80,0xbc498000,0x3f7e3f7f,0xbde2bdc9,0x3f803f80,0xbd17bcc9,0x3f7e3f7e,0xbe0abdfb,0x3f803f80,0xbd7bbd49,0x3f7d3f7d,0xbe23be16,
0x3f7f3f7f,0xbdb0bd97,0x3f7c3f7c,0xbe3bbe2f,0x3f803f80,0xbc978000,0x3f7c3f7d,0xbe29be16,0x3f803f80,0xbd62bd17,0x3f7b3f7c,0xbe4ebe3b,
0x3f7f3f7f,0xbdbcbd97,0x3f793f7a,0xbe73be60,0x3f7e3f7e,0xbe04bde2,0x3f763f78,0xbe8cbe82,0x3f803f80,0xbcc98000,0x3f7a3f7b,0xbe60be48,
0x3f7f3f80,0xbd97bd49,0x3f773f78,0xbe89be79,0x3f7e3f7f,0xbdfbbdc9,0x3f733f75,0xbea1be95,0x3f7c3f7d,0xbe2fbe16,0x3f6f3f71,0xbeb8beac,
0x3f803f80,0xbcfb8000,0x3f763f78,0xbe8cbe79,0x3f7f3f80,0xbdbcbd7b,0x3f723f74,0xbeaabe9b,0x3f7d3f7e,0xbe1cbdfb,0x3f6c3f6f,0xbec7beb8,
0x3f7a3f7c,0xbe5abe3b,0x3f653f69,0xbee3bed5,0x3f803f80,0xbd178000,0x3f723f75,0xbea7be95,0x3f7e3f7f,0xbde2bd97,0x3f6b3f6f,0xbecabeb8,
0x3f7c3f7d,0xbe3bbe16,0x3f633f67,0xbeecbedb,0x3f783f7a,0xbe82be60,0x3f5a3f5f,0xbf06befc,0x3f803f80,0xbd308000,0x3f6d3f71,0xbec1beac,
0x3f7e3f7f,0xbe04bdb0,0x3f643f69,0xbee9bed5,0x3f7a3f7c,0xbe5abe2f,0x3f593f5f,0xbf08befc,0x3f753f78,0xbe98be82,0x3f4d3f53,0xbf1abf11,
0x3f803f80,0x80008000,0x3f803f80,0x80008000,0x3f803f80,0x80008000,0x3f803f80,0x80008000,0x3f803f80,0x80008000,0x3f803f80,0x80008000,
0x3f803f80,0x80008000,0x3f803f80,0x80008000,0x3f7f3f7f,0xbdd5bdc9,0x3f7d3f7d,0xbe1cbe16,0x3f7e3f7e,0xbdeebde2,0x3f7c3f7d,0xbe29be23,
0x3f7e3f7e,0xbe04bdfb,0x3f7c3f7c,0xbe35be2f,0x3f7d3f7e,0xbe10be0a,0x3f7b3f7c,0xbe42be3b,0x3f7a3f7b,0xbe54be48,0x3f743f75,0xbe9bbe95,
0x3f793f7a,0xbe6dbe60,0x3f723f73,0xbea7bea1,0x3f783f78,0xbe82be79,0x3f703f71,0xbeb2beac,0x3f763f77,0xbe8fbe89,0x3f6e3f6f,0xbebebeb8,
0x3f743f75,0xbe9ebe95,0x3f653f67,0xbee3bedb,0x3f713f72,0xbeafbea7,0x3f613f63,0xbef4beec,0x3f6d3f6f,0xbec1beb8,0x3f5c3f5f,0xbf02befc,
0x3f693f6b,0xbed2beca,0x3f573f5a,0xbf0abf06,0x3f6a3f6d,0xbecfbec4,0x3f513f55,0xbf13bf0e,0x3f653f67,0xbee6bedb,0x3f4a3f4e,0xbf1dbf18,
0x3f5f3f62,0xbefcbef1,0x3f423f46,0xbf27bf22,0x3f583f5c,0xbf09bf04,0x3f393f3e,0xbf31bf2c,0x3f5e3f62,0xbeffbef1,0x3f383f3e,0xbf32bf2c,
0x3f563f5a,0xbf0dbf06,0x3f2d3f33,0xbf3dbf37,0x3f4d3f51,0xbf1abf13,0x3f213f27,0xbf47bf42,0x3f433f48,0xbf26bf20,0x3f153f1b,0xbf50bf4c,
0x3f4f3f55,0xbf16bf0e,0x3f1b3f22,0xbf4cbf46,0x3f443f4a,0xbf25bf1d,0x3f0c3f13,0xbf57bf51,0x3f373f3e,0xbf33bf2c,0x3ef73f04,0xbf60bf5c,
0x3f2a3f31,0xbf40bf39,0x3ed53ee6,0xbf69bf65,0x3f3f3f46,0xbf2bbf22,0x3ef43f04,0xbf61bf5c,0x3f2f3f37,0xbf3abf33,0x3ecd3ee1,0xbf6bbf66,
0x3f1f3f27,0xbf49bf42,0x3ea43eb8,0xbf73bf6f,0x3f0d3f16,0xbf56bf4f,0x3e733e8f,0xbf79bf76,0x3f803f80,0xbd498000,0x3f673f6d,0xbedbbec4,
0x3f7d3f7f,0xbe16bdc9,0x3f5c3f62,0xbf04bef1,0x3f783f7b,0xbe79be48,0x3f4e3f55,0xbf18bf0e,0x3f713f75,0xbeacbe95,0x3f3e3f46,0xbf2cbf22,
0x3f803f80,0xbd628000,0x3f613f67,0xbef4bedb,0x3f7c3f7e,0xbe29bde2,0x3f523f5a,0xbf12bf06,0x3f763f7a,0xbe8cbe60,0x3f413f4a,0xbf28bf1d,
0x3f6d3f72,0xbec1bea7,0x3f2d3f37,0xbf3dbf33,0x3f803f80,0xbd7b8000,0x3f5a3f62,0xbf06bef1,0x3f7c3f7e,0xbe3bbdfb,0x3f483f51,0xbf20bf13,
0x3f743f78,0xbe9bbe79,0x3f333f3e,0xbf37bf2c,0x3f693f6f,0xbed5beb8,0x3f1b3f27,0xbf4cbf42,0x3f7f3f80,0xbd8a8000,0x3f523f5c,0xbf12bf04,
0x3f7b3f7e,0xbe4ebe0a,0x3f3d3f48,0xbf2dbf20,0x3f723f77,0xbeaabe89,0x3f243f31,0xbf45bf39,0x3f643f6b,0xbee9beca,0x3f083f16,0xbf59bf4f,
0x3f7f3f80,0xbd978000,0x3f4a3f55,0xbf1dbf0e,0x3f7a3f7d,0xbe60be16,0x3f313f3e,0xbf39bf2c,0x3f6f3f75,0xbeb8be95,0x3f133f22,0xbf51bf46,
0x3f5f3f67,0xbefcbedb,0x3ee63f04,0xbf65bf5c,0x3f7f3f80,0xbda38000,0x3f413f4e,0xbf28bf18,0x3f793f7d,0xbe73be23,0x3f243f33,0xbf45bf37,
0x3f6c3f73,0xbec7bea1,0x3f023f13,0xbf5cbf51,0x3f593f63,0xbf08beec,0x3ebb3ee1,0xbf6ebf66,0x3f7f3f80,0xbdb08000,0x3f373f46,0xbf33bf22,
0x3f783f7c,0xbe82be2f,0x3f163f27,0xbf4fbf42,0x3f693f71,0xbed5beac,0x3ee13f04,0xbf66bf5c,0x3f533f5f,0xbf11befc,0x3e8f3eb8,0xbf76bf6f,
0x3f7f3f80,0xbdbc8000,0x3f2d3f3e,0xbf3dbf2c,0x3f763f7c,0xbe8cbe3b,0x3f083f1b,0xbf59bf4c,0x3f653f6f,0xbee3beb8,0x3ebb3ee6,0xbf6ebf65,
0x3f4d3f5a,0xbf1abf06,0x3e423e8f,0xbf7bbf76,0x3f2c3f35,0xbf3ebf35,0x3eac3ec4,0xbf71bf6d,0x3f183f22,0xbf4ebf46,0x3e793e95,0xbf78bf75,
0x3f043f0e,0xbf5cbf55,0x3e163e48,0xbf7dbf7b,0x3edb3ef1,0xbf67bf62,0x3d493dc9,0xbf80bf7f,0x3f173f22,0xbf4fbf46,0x3e423e79,0xbf7bbf78,
0x3eff3f0c,0xbf5ebf57,0x3da33e0a,0xbf7fbf7e,0x3ecd3ee6,0xbf6bbf65,0xbcfb3cc9,0xbf80bf80,0x3e983eb2,0xbf75bf70,0xbe10bdb0,0xbf7dbf7f,
0x3f013f0e,0xbf5dbf55,0x3d173dc9,0xbf80bf7f,0x3eca3ee6,0xbf6bbf65,0xbdb0bcc9,0xbf7fbf80,0x3e8f3eac,0xbf76bf71,0xbe54be16,0xbf7abf7d,
0x3e233e60,0xbf7dbf7a,0xbea7be89,0xbf72bf77,0x3ed23ef1,0xbf69bf62,0xbdeebd49,0xbf7ebf80,0x3e923eb2,0xbf75bf70,0xbe7fbe3b,0xbf78bf7c,
0x3e1c3e60,0xbf7dbf7a,0xbec1bea1,0xbf6dbf73,0x3c973db0,0xbf80bf7f,0xbeffbee1,0xbf5ebf66,0x3ea13ec4,0xbf73bf6d,0xbe89be48,0xbf77bf7b,
0x3e2f3e79,0xbf7cbf78,0xbecfbeac,0xbf6abf71,0x3cc93dc9,0xbf80bf7f,0xbf09bef1,0xbf58bf62,0xbdfbbd49,0xbf7ebf80,0xbf27bf18,0xbf42bf4e,
0x3e5a3e95,0xbf7abf75,0xbed2beac,0xbf69bf71,0x3d623e0a,0xbf80bf7e,0xbf0dbef7,0xbf56bf60,0xbdd5bcc9,0xbf7fbf80,0xbf2dbf1d,0xbf3dbf4a,
0xbe86be3b,0xbf77bf7c,0xbf49bf3c,0xbf1fbf2e,0x3de23e48,0xbf7ebf7b,0xbf0cbef1,0xbf57bf62,0xbd7b3cc9,0xbf80bf80,0xbf2ebf1d,0xbf3cbf4a,
0xbe6dbe16,0xbf79bf7d,0xbf4cbf3e,0xbf1bbf2c,0xbecabea1,0xbf6bbf73,0xbf63bf58,0xbeecbf09,0x3bc93dc9,0xbf80bf7f,0xbf2bbf18,0xbf3fbf4e,
0xbe35bdb0,0xbf7cbf7f,0xbf4bbf3c,0xbf1cbf2e,0xbeb5be89,0xbf6fbf77,0xbf64bf58,0xbee9bf09,0xbf05bee1,0xbf5bbf66,0xbf75bf6e,0xbe92bebe,
0x3f7f3f80,0xbdc98000,0x3f223f35,0xbf46bf35,0x3f753f7b,0xbe95be48,0x3ef13f0e,0xbf62bf55,0x3f623f6d,0xbef1bec4,0x3e953ec4,0xbf75bf6d,
0x3f463f55,0xbf22bf0e,0x3dc93e48,0xbf7fbf7b,0x3f7f3f80,0xbdd58000,0x3f173f2c,0xbf4fbf3e,0x3f743f7a,0xbe9ebe54,0x3ed23f01,0xbf69bf5d,
0x3f5e3f6a,0xbeffbecf,0x3e5a3ea1,0xbf7abf73,0x3f3f3f4f,0xbf2bbf16,0x3bc93de2,0xbf80bf7e,0x3f7e3f80,0xbde28000,0x3f0c3f22,0xbf57bf46,
0x3f723f7a,0xbea7be60,0x3eb23ee6,0xbf70bf65,0x3f5a3f67,0xbf06bedb,0x3e0a3e79,0xbf7ebf78,0x3f373f4a,0xbf33bf1d,0xbdb03cc9,0xbf7fbf80,
0x3f7e3f80,0xbdee8000,0x3eff3f18,0xbf5ebf4e,0x3f713f79,0xbeafbe6d,0x3e923eca,0xbf75bf6b,0x3f563f65,0xbf0dbee6,0x3d623e2f,0xbf80bf7c,
0x3f2f3f44,0xbf3abf25,0xbe35bd7b,0xbf7cbf80,0x3f7e3f80,0xbdfb8000,0x3ee63f0e,0xbf65bf55,0x3f6f3f78,0xbeb8be79,0x3e603eac,0xbf7abf71,
0x3f513f62,0xbf13bef1,0xbcc93dc9,0xbf80bf7f,0x3f273f3e,0xbf42bf2c,0xbe89be16,0xbf77bf7d,0x3f7e3f80,0xbe048000,0x3ecd3f04,0xbf6bbf5c,
0x3f6d3f78,0xbec1be82,0x3e1c3e8f,0xbf7dbf76,0x3f4d3f5f,0xbf1abefc,0xbdd53cc9,0xbf7fbf80,0x3f1f3f37,0xbf49bf33,0xbeb5be6d,0xbf6fbf79,
0x3f7e3f80,0xbe0a8000,0x3eb23ef1,0xbf70bf62,0x3f6b3f77,0xbecabe89,0x3db03e60,0xbf7fbf7a,0x3f483f5c,0xbf20bf04,0xbe3bbd49,0xbf7cbf80,
0x3f163f31,0xbf4fbf39,0xbee1bea1,0xbf66bf73,0x3f7d3f80,0xbe108000,0x3e983edb,0xbf75bf67,0x3f693f76,0xbed2be8f,0x3c973e23,0xbf80bf7d,
0x3f433f58,0xbf26bf09,0xbe86bdfb,0xbf77bf7e,0x3f0d3f2a,0xbf56bf40,0xbf05beca,0xbf5bbf6b,0xbdc90000,0xbf7fbf80,0xbf46bf35,0xbf22bf35,
0xbe95be48,0xbf75bf7b,0xbf62bf55,0xbef1bf0e,0xbef1bec4,0xbf62bf6d,0xbf75bf6d,0xbe95bec4,0xbf22bf0e,0xbf46bf55,0xbf7fbf7b,0xbdc9be48,
0xbe4ebdc9,0xbf7bbf7f,0xbf5cbf4e,0xbf02bf18,0xbecdbe9b,0xbf6bbf74,0xbf73bf69,0xbea4bed5,0xbf15befc,0xbf50bf5f,0xbf7ebf7a,0xbdeebe60,
0xbf3dbf2a,0xbf2dbf40,0xbf7fbf80,0x3dbcbc49,0xbe9bbe48,0xbf74bf7b,0xbf6ebf62,0xbebebef1,0xbf01becf,0xbf5dbf6a,0xbf7dbf77,0xbe23be89,
0xbf2ebf18,0xbf3cbf4e,0xbf80bf80,0x3d7bbd49,0xbf53bf42,0xbf11bf27,0xbf76bf7c,0x3e8f3e2f,0xbecdbe95,0xbf6bbf75,0xbf79bf71,0xbe66beac,
0xbf1abf01,0xbf4dbf5d,0xbf80bf7e,0x3bc9bde2,0xbf45bf31,0xbf24bf39,0xbf79bf7e,0x3e733dfb,0xbf65bf57,0xbee3bf0c,0xbf64bf70,0x3ee93eb2,
0xbefcbec4,0xbf5fbf6d,0xbf7fbf7b,0xbd97be48,0xbf31bf18,0xbf39bf4e,0xbf7cbf80,0x3e2f3d49,0xbf58bf46,0xbf09bf22,0xbf6abf75,0x3ecf3e95,
0xbf73bf67,0xbea1bedb,0xbf4abf5c,0x3f1d3f04,0xbf15bef1,0xbf50bf62,0xbf7fbf80,0x3da3bd49,0xbf45bf2e,0xbf24bf3c,0xbf72bf7a,0x3eaa3e54,
0xbf68bf58,0xbed8bf09,0xbf54bf65,0x3f103ee6,0xbf7cbf74,0xbe35be9b,0xbf28bf40,0x3f413f2a,0xbf2abf0e,0xbf40bf55,0xbf79bf7f,0x3e6d3dc9,
0xbf57bf42,0xbf0cbf27,0xbf60bf6f,0x3ef73eb8,0xbf74bf67,0xbe9bbedb,0xbf37bf4e,0x3f333f18,0xbf80bf7c,0xbd17be2f,0xbf01bf1d,0x3f5d3f4a,
0xbf3dbf22,0xbf2dbf46,0xbf6dbf78,0x3ec13e79,0xbf65bf53,0xbee3bf11,0xbf49bf5d,0x3f1f3f01,0xbf7cbf73,0xbe35bea1,0xbf15bf31,0x3f503f39,
0xbf7fbf80,0x3dd5bd17,0xbeaabeec,0x3f723f63,0x3f7d3f80,0xbe168000,0x3e793ec4,0xbf78bf6d,0x3f673f75,0xbedbbe95,0xbd493dc9,0xbf80bf7f,
0x3f3e3f55,0xbf2cbf0e,0xbeacbe48,0xbf71bf7b,0x3f043f22,0xbf5cbf46,0xbf18bef1,0xbf4ebf62,0x3f7d3f80,0xbe1c8000,0x3e423eac,0xbf7bbf71,
0x3f653f74,0xbee3be9b,0xbdee3d17,0xbf7ebf80,0x3f383f51,0xbf32bf13,0xbed2be89,0xbf69bf77,0x3ef43f1b,0xbf61bf4c,0xbf2bbf0c,0xbf3fbf57,
0x3f7d3f80,0xbe238000,0x3e0a3e95,0xbf7ebf75,0x3f633f73,0xbeecbea1,0xbe3bbcc9,0xbf7cbf80,0x3f333f4e,0xbf37bf18,0xbef7beac,0xbf60bf71,
0x3ee13f13,0xbf66bf51,0xbf3cbf1d,0xbf2ebf4a,0x3f7c3f80,0xbe298000,0x3da33e79,0xbf7fbf78,0x3f613f72,0xbef4bea7,0xbe7fbdb0,0xbf78bf7f,
0x3f2d3f4a,0xbf3dbf1d,0xbf0dbecf,0xbf56bf6a,0x3ecd3f0c,0xbf6bbf57,0xbf4bbf2e,0xbf1cbf3c,0x3f7c3f80,0xbe2f8000,0x3cc93e48,0xbf80bf7b,
0x3f5f3f71,0xbefcbeac,0xbea1be16,0xbf73bf7d,0x3f273f46,0xbf42bf22,0xbf1dbef1,0xbf4abf62,0x3eb83f04,0xbf6fbf5c,0xbf58bf3e,0xbf09bf2c,
0x3f7c3f80,0xbe358000,0xbcfb3e16,0xbf80bf7d,0x3f5c3f70,0xbf02beb2,0xbec1be54,0xbf6dbf7a,0x3f213f42,0xbf47bf27,0xbf2dbf09,0xbf3dbf58,
0x3ea43ef7,0xbf73bf60,0xbf64bf4c,0xbee9bf1b,0x3f7c3f80,0xbe3b8000,0xbdb03dc9,0xbf7fbf7f,0x3f5a3f6f,0xbf06beb8,0xbee1be89,0xbf66bf77,
0x3f1b3f3e,0xbf4cbf2c,0xbf3cbf18,0xbf2ebf4e,0x3e8f3ee6,0xbf76bf65,0xbf6ebf58,0xbebebf09,0x3f7b3f80,0xbe428000,0xbe103d49,0xbf7dbf80,
0x3f573f6e,0xbf0abebe,0xbeffbea7,0xbf5ebf72,0x3f153f39,0xbf50bf31,0xbf49bf27,0xbf1fbf42,0x3e733ed5,0xbf79bf69,0xbf75bf63,0xbe92beec,
0xbf4ebf35,0xbf18bf35,0xbf5cbf6d,0x3f043ec4,0xbf71bf62,0xbeacbef1,0xbf2cbf46,0x3f3e3f22,0xbf80bf7b,0xbd49be48,0xbedbbf0e,0x3f673f55,
0xbf78bf7f,0x3e793dc9,0xbe16be95,0x3f7d3f75,0xbf5cbf46,0xbf02bf22,0xbf45bf5c,0x3f243f04,0xbf79bf6e,0xbe66bebe,0xbf0abf2a,0x3f573f40,
0xbf7fbf7f,0x3da3bd97,0xbe86becf,0x3f773f6a,0xbf6dbf79,0x3ec13e6d,0x3d30bde2,0x3f803f7e,0xbf69bf55,0xbed5bf0e,0xbf2abf46,0x3f403f22,
0xbf7ebf77,0xbde2be89,0xbecabf09,0x3f6b3f58,0xbf7abf80,0x3e543d49,0xbdb0be79,0x3f7f3f78,0xbf5dbf6f,0x3f013eb8,0x3e6d3d97,0x3f793f7f,
0xbf73bf62,0xbea4bef1,0xbf0abf2c,0x3f573f3e,0xbf80bf7d,0x3bc9be23,0xbe73beca,0x3f793f6b,0xbf72bf7c,0x3eaa3e2f,0x3dbcbd97,0x3f7f3f7f,
0xbf49bf60,0x3f1f3ef7,0x3ed23e82,0x3f693f78,0xbf7abf6d,0xbe60bec4,0xbecfbf0e,0x3f6a3f55,0xbf7ebf80,0x3dfbbd49,0xbd97be79,0x3f7f3f78,
0xbf65bf75,0x3ee63e95,0x3e893dc9,0x3f773f7f,0xbf31bf4e,0x3f393f18,0x3f133edb,0x3f513f67,0xbf7ebf75,0xbdeebe95,0xbe86bedb,0x3f773f67,
0xbf79bf80,0x3e733d7b,0x3dbcbdb0,0x3f7f3f7f,0xbf54bf6a,0x3f103ecf,0x3ede3e89,0x3f673f77,0xbf15bf37,0x3f503f33,0x3f383f16,0x3f323f4f,
0xbf80bf7b,0xbc49be48,0xbde2be95,0x3f7e3f75,0xbf70bf7c,0x3eb23e2f,0x3e823d97,0x3f783f7f,0xbf40bf5c,0x3f2a3f04,0x3f163edb,0x3f4f3f67,
0xbeecbf1d,0x3f633f4a,0x3f573f39,0x3f0c3f31,0xbf7fbf7f,0x3dbcbdc9,0x3d30be16,0x3f803f7d,0xbf64bf76,0x3ee93e8f,0x3ed23e6d,0x3f693f79,
0xbf28bf4a,0x3f413f1d,0x3f383f13,0x3f323f51,0xbeaabf01,0x3f723f5d,0x3f6d3f57,0x3ec13f0c,
};
__device__ const __align__(128) uint64_t c_inv[16384] = {
0x3f003f003f003f00,0x3f003f003f003f00,0x3f003f003f003f00,0x3f003f003f003f00,0x3f003f003f003f00,0x3f003f003f003f00,0x3f003f003f003f00,0x3f003f003f003f00,
0xbf003f00bf003f00,0xbf003f00bf003f00,0xbf003f00bf003f00,0xbf003f00bf003f00,0xbf003f00bf003f00,0xbf003f00bf003f00,0xbf003f00bf003f00,0xbf003f00bf003f00,
0x3f773f783f7a3f7b,0x3f6f3f713f733f75,0x3f7f3f803f803f80,0x3f7c3f7d3f7e3f7f,0x3f4a3f4e3f513f55,0x3f393f3e3f423f46,0x3f653f673f6a3f6d,0x3f583f5c3f5f3f62,
0xbe89be79be60be48,0xbeb8beacbea1be95,0xbd97bd49bcc98000,0xbe2fbe16bdfbbdc9,0xbf1dbf18bf13bf0e,0xbf31bf2cbf27bf22,0xbee6bedbbecfbec4,0xbf09bf04befcbef1,
0x3f183f223f2c3f35,0x3edb3ef13f043f0e,0x3e793e953eac3ec4,0x3d493dc93e163e48,0x3f7d3f7f3f803f80,0x3f713f753f783f7b,0x3f5c3f623f673f6d,0x3f3e3f463f4e3f55,
0xbf4ebf46bf3ebf35,0xbf67bf62bf5cbf55,0xbf78bf75bf71bf6d,0xbf80bf7fbf7dbf7b,0xbe16bdc9bd498000,0xbeacbe95be79be48,0xbf04bef1bedbbec4,0xbf2cbf22bf18bf0e,
0xbecfbeacbe89be48,0xbf27bf18bf09bef1,0x3e2f3e793ea13ec4,0xbdfbbd493cc93dc9,0x3f313f3e3f4a3f55,0x3ee63f043f133f22,0x3f7a3f7d3f7f3f80,0x3f5f3f673f6f3f75,
0xbf6abf71bf77bf7b,0xbf42bf4ebf58bf62,0xbf7cbf78bf73bf6d,0xbf7ebf80bf80bf7f,0xbf39bf2cbf1dbf0e,0xbf65bf5cbf51bf46,0xbe60be16bd978000,0xbefcbedbbeb8be95,
0x3f753f7b3f7f3f80,0x3f463f553f623f6d,0x3ef13f0e3f223f35,0x3dc93e483e953ec4,0xbe95be48bdc90000,0xbf22bf0ebef1bec4,0xbf62bf55bf46bf35,0xbf7fbf7bbf75bf6d,
0xbe95be48bdc98000,0xbf22bf0ebef1bec4,0xbf62bf55bf46bf35,0xbf7fbf7bbf75bf6d,0xbf75bf7bbf7fbf80,0xbf46bf55bf62bf6d,0xbef1bf0ebf22bf35,0xbdc9be48be95bec4,
0x3e603eac3ee63f0e,0xbe89be16bcc93dc9,0x3f6f3f783f7e3f80,0x3f273f3e3f513f62,0xbf7cbf80bf7fbf7b,0xbf4abf5cbf6abf75,0xbf31bf18befcbec4,0xbf73bf67bf58bf46,
0xbf7abf71bf65bf55,0xbf77bf7dbf80bf7f,0xbeb8be79bdfb8000,0xbf42bf2cbf13bef1,0x3e2f3d49bd97be48,0x3f1d3f043ecf3e95,0xbf39bf4ebf5fbf6d,0xbea1bedbbf09bf22,
0xbf71bf62bf4ebf35,0xbf78bf7fbf80bf7b,0xbf2cbf46bf5cbf6d,0xbe16be95bedbbf0e,0x3f673f753f7d3f80,0x3f043f223f3e3f55,0xbd493dc93e793ec4,0xbf18bef1beacbe48,
0xbeacbef1bf18bf35,0x3e793dc9bd49be48,0x3f3e3f223f043ec4,0x3f7d3f753f673f55,0xbedbbe95be168000,0xbf5cbf46bf2cbf0e,0xbf80bf7fbf78bf6d,0xbf4ebf62bf71bf7b,
0xbd97be79becfbf0e,0x3f133edb3e893dc9,0xbf7ebf80bf7abf6d,0xbf31bf4ebf65bf75,0xbea1be163cc93e48,0xbf58bf3ebf1dbef1,0x3f5f3f713f7c3f80,0x3eb83f043f273f46,
0x3f7f3f783f6a3f55,0x3f513f673f773f7f,0x3dfbbd49be60bec4,0x3f393f183ee63e95,0xbf73bf7dbf80bf7b,0xbf09bf2cbf4abf62,0xbefcbeacbe2f8000,0xbf6fbf5cbf42bf22,
0x3f553f6d3f7b3f80,0x3e483ec43f0e3f35,0xbf0ebec4be480000,0xbf7bbf6dbf55bf35,0xbf55bf6dbf7bbf80,0xbe48bec4bf0ebf35,0x3f0e3ec43e480000,0x3f7b3f6d3f553f35,
0xbf0ebec4be488000,0xbf7bbf6dbf55bf35,0xbf55bf6dbf7bbf80,0xbe48bec4bf0ebf35,0x3f0e3ec43e488000,0x3f7b3f6d3f553f35,0x3f553f6d3f7b3f80,0x3e483ec43f0e3f35,
0xbf42bf18becfbe48,0xbf7cbf80bf77bf62,0x3f4a3f673f7a3f80,0x3cc93e793ee63f22,0x3f733f5c3f393f0e,0x3f583f713f7e3f7f,0xbefcbf2cbf51bf6d,0x3eb83e16bd97be95,
0xbf27bf4ebf6abf7b,0x3e2fbd49be89bef1,0xbf1dbedbbe608000,0xbf80bf78bf65bf46,0x3ea13f043f313f55,0xbf09beacbdfb3dc9,0x3f5f3f3e3f133ec4,0x3f6f3f7d3f7f3f75,
0xbd49be95bf04bf35,0x3f4e3f223edb3e48,0x3f713f7f3f7d3f6d,0x3e793ef13f2c3f55,0x3f3e3f623f783f80,0xbe163dc93eac3f0e,0xbf67bf46bf18bec4,0xbf5cbf75bf80bf7b,
0x3f803f753f5c3f35,0x3f183f463f673f7b,0xbeacbdc93e163ec4,0xbf78bf62bf3ebf0e,0xbf2cbef1be798000,0xbf7dbf7fbf71bf55,0xbedbbf22bf4ebf6d,0x3f043e953d49be48,
0x3f093f3e3f653f7b,0xbefcbe793cc93e95,0x3ecf3e16bdfbbec4,0x3f7f3f713f513f22,0xbf7cbf67bf42bf0e,0xbf1dbf4ebf6fbf7f,0x3f313f5c3f773f80,0xbea1bd493e603ef1,
0xbf58bf2cbee6be48,0xbf5fbf78bf80bf75,0x3f6a3f7d3f7e3f6d,0x3d973eac3f133f46,0xbe2fbedbbf27bf55,0x3f4a3f183eb83dc9,0xbf39bf04be898000,0xbf73bf80bf7abf62,
0x3f223f553f753f80,0xbef1be483dc93ec4,0xbf7fbf7bbf62bf35,0xbe95bf0ebf46bf6d,0x3f463f0e3e950000,0x3f623f7b3f7f3f6d,0xbdc93e483ef13f35,0xbf75bf55bf22bec4,
0xbf46bf0ebe958000,0xbf62bf7bbf7fbf6d,0x3dc9be48bef1bf35,0x3f753f553f223ec4,0x3f223f553f753f80,0xbef1be483dc93ec4,0xbf7fbf7bbf62bf35,0xbe95bf0ebf46bf6d,
0xbf6fbf80bf77bf55,0x3d97be79bf09bf46,0x3f133f4e3f733f80,0xbf1dbeacbcc93e95,0xbf31bedbbdfb3e48,0xbf65bf7dbf7cbf62,0x3f7a3f5c3f273ec4,0x3efc3f3e3f6a3f7f,
0x3eb83d49be89bf0e,0x3f7f3f783f583f22,0xbf51bf18bea18000,0xbf4abf71bf80bf75,0xbf39bf67bf7ebf7b,0x3ee63e16be2fbef1,0x3e603f043f423f6d,0xbf5fbf2cbecfbdc9,
0x3f783f7f3f673f35,0xbd493e953f183f55,0xbf7dbf62bf2cbec4,0xbeacbf22bf5cbf7b,0x3f043f463f713f80,0xbf3ebef1be163e48,0xbf4ebf75bf80bf6d,0x3edb3dc9be79bf0e,
0xbe793dc93edb3f35,0xbf80bf75bf4ebf0e,0xbe16bef1bf3ebf6d,0x3f713f463f043e48,0xbf5cbf22beac8000,0xbf2cbf62bf7dbf7b,0x3f183e95bd49bec4,0x3f673f7f3f783f55,
0xbf5fbf7dbf7abf55,0x3ecf3d49bea1bf22,0x3f423f713f803f6d,0xbf13be793dfb3ef1,0xbf1dbf5cbf7cbf7b,0x3f393edb3d97be95,0x3ee63f3e3f6f3f80,0xbf58bf18be893dc9,
0x3efc3e16be60bf0e,0x3f6a3f803f733f46,0xbf27beac3cc93ec4,0xbf51bf78bf7ebf62,0x3f4a3f043e2fbe48,0x3f313f673f7f3f75,0xbf65bf2cbeb88000,0xbf09bf4ebf77bf7f,
0x3ec43f353f6d3f80,0xbf6dbf35bec40000,0xbec4bf35bf6dbf80,0x3f6d3f353ec40000,0x3ec43f353f6d3f80,0xbf6dbf35bec40000,0xbec4bf35bf6dbf80,0x3f6d3f353ec40000,
0xbf6dbf35bec48000,0xbec4bf35bf6dbf80,0x3f6d3f353ec48000,0x3ec43f353f6d3f80,0xbf6dbf35bec48000,0xbec4bf35bf6dbf80,0x3f6d3f353ec48000,0x3ec43f353f6d3f80,
0xbdfbbf04bf51bf7b,0x3f803f673f273e95,0x3ea13f2c3f6a3f80,0xbf7abf4ebefcbdc9,0x3e89be16bf09bf55,0x3f6f3f803f653f22,0xbd973eac3f313f6d,0xbf7cbf78bf4abef1,
0x3f7e3f5c3f133e48,0x3cc93edb3f423f75,0xbf73bf3ebecf8000,0xbe60bf18bf5fbf7f,0x3f773f7d3f583f0e,0xbeb83d493ee63f46,0xbf7fbf71bf39bec4,0x3e2fbe79bf1dbf62,
0xbf04bdc93eac3f35,0xbf3ebf75bf7dbf55,0x3f4e3ef13d49bec4,0x3edb3f463f783f7b,0x3e793f223f673f80,0xbf80bf62bf18be48,0x3e16be95bf2cbf6d,0x3f713f7f3f5c3f0e,
0xbf5cbf7fbf71bf35,0x3f2c3e95be16bf0e,0x3f183f623f803f6d,0xbf67bf22be793e48,0xbf78bf46bedb8000,0xbd49bef1bf4ebf7b,0x3f7d3f753f3e3ec4,0xbeac3dc93f043f55,
0x3f803f673f1d3e48,0xbea13e163f133f62,0xbf58bf04bd973ec4,0xbe89bf2cbf6fbf7f,0x3ecfbd49befcbf55,0x3f423f783f7a3f46,0x3e2f3f183f653f80,0xbf7ebf71bf31be95,
0xbcc93edb3f4a3f7b,0xbf73bf7dbf51bef1,0xbf09bf5cbf7fbf6d,0x3f773f3e3eb8bdc9,0x3f6a3f803f5f3f0e,0xbf27be793e603f22,0xbf7cbf4ebee68000,0x3dfbbeacbf39bf75,
0x3dc93f0e3f623f80,0xbf75bf7bbf46bec4,0x3f223e48be95bf35,0x3ef13f553f7f3f6d,0xbf7fbf55bef10000,0x3e95be48bf22bf6d,0x3f463f7b3f753f35,0xbf62bf0ebdc93ec4,
0xbf7fbf55bef18000,0x3e95be48bf22bf6d,0x3f463f7b3f753f35,0xbf62bf0ebdc93ec4,0xbdc9bf0ebf62bf80,0x3f753f7b3f463ec4,0xbf22be483e953f35,0xbef1bf55bf7fbf6d,
0x3f513edbbd97bf0e,0x3dfb3f183f6a3f7f,0x3cc93f043f5f3f80,0xbf65bf80bf58bef1,0x3e603f2c3f733f7b,0xbf77bf78bf39be95,0xbf6fbf7dbf4abec4,0x3f423eacbe2fbf22,
0x3f133f673f7f3f55,0xbf7ebf4ebecf3dc9,0xbf80bf5cbefc8000,0x3ee6bd49bf09bf62,0xbf7abf3ebea13e48,0x3e89be79bf31bf75,0x3eb8be16bf1dbf6d,0x3f273f713f7c3f46,
0xbf2cbf75bf78bf35,0x3f7d3f463eacbe48,0xbedb3dc93f183f6d,0xbf04bf62bf80bf55,0xbd493ef13f5c3f80,0xbf4ebf7fbf67bf0e,0x3f713f223e16bec4,0xbe793e953f3e3f7b,
0x3f3e3e95be79bf35,0x3e163f223f713f7b,0xbf67bf7fbf4ebec4,0x3f5c3ef1bd49bf0e,0xbf80bf62bf048000,0x3f183dc9bedbbf55,0x3eac3f463f7d3f6d,0xbf78bf75bf2cbe48,
0xbf65bf043cc93f0e,0x3e60beacbf4abf7f,0xbe89bf3ebf7cbf6d,0x3f6a3f7d3f423e95,0x3f7f3f4e3eb8be48,0xbf13bd493efc3f62,0xbdfb3edb3f583f80,0xbf31bf78bf73bf22,
0xbee6bf5cbf80bf55,0x3f7a3f713f1d3dc9,0x3f773f2c3e2fbec4,0xbecf3e163f273f75,0x3d973f183f6f3f7b,0xbf51bf80bf5fbef1,0xbf7ebf67bf098000,0x3f393e79bea1bf46,
0xbe483ec43f553f80,0xbf0ebf6dbf7bbf35,0x3f7b3f6d3f0e0000,0xbf55bec43e483f35,0x3e48bec4bf55bf80,0x3f0e3f6d3f7b3f35,0xbf7bbf6dbf0e0000,0x3f553ec4be48bf35,
0xbf7bbf6dbf0e8000,0x3f553ec4be48bf35,0xbe483ec43f553f80,0xbf0ebf6dbf7bbf35,0x3f7b3f6d3f0e8000,0xbf55bec43e483f35,0x3e48bec4bf55bf80,0x3f0e3f6d3f7b3f35,
0x3f653f7d3f393e48,0xbf7abf2cbdfb3ef1,0xbe893eac3f513f80,0xbecfbf5cbf7fbf46,0xbf27bf78bf6fbf0e,0x3f7c3f673efcbdc9,0x3f1d3d49bf09bf6d,0x3cc93f183f733f75,
0xbee63e163f313f7b,0xbe60bf3ebf7ebf62,0xbf77bf71bf138000,0x3f6a3f04bd97bf22,0x3f423e79beb8bf55,0xbe2f3edb3f5f3f7f,0x3f4a3f803f583ec4,0xbf80bf4ebea13e95,
0x3f673ef1be16bf35,0xbf043dc93f2c3f7b,0xbd49bf22bf78bf6d,0x3f183f753f713f0e,0xbeac3e953f4e3f80,0xbe79bf46bf80bf55,0x3f3e3f7f3f5c3ec4,0xbf7dbf62bedb3e48,
0x3edb3f623f7d3f35,0xbf5cbf7fbf3ebe48,0x3f803f463e79bec4,0xbf4ebe953eac3f55,0xbf71bf75bf188000,0x3f783f223d49bf0e,0xbf2cbdc93f043f6d,0x3e16bef1bf67bf7b,
0x3f13bd49bf27bf7b,0xbdfb3f043f6f3f75,0x3f803f4e3e89bec4,0xbf65bedb3e603f46,0x3f093f713f733f0e,0xbf5fbf7dbf31bdc9,0xbecf3e793f4a3f80,0xbd97bf2cbf7cbf62,
0x3f513f803f423e48,0xbf7ebf5cbeb83e95,0xbcc93f183f773f6d,0xbee6bf67bf7abf22,0xbf58beac3ea13f55,0x3efcbe16bf39bf7f,0xbf6abf78bf1d8000,0x3f7f3f3e3e2fbef1,
0xbef13e483f463f80,0x3dc9bf0ebf75bf6d,0x3e953f553f7f3f35,0xbf22bf7bbf62bec4,0x3f623f7b3f220000,0xbf7fbf55be953ec4,0x3f753f0ebdc9bf35,0xbf46be483ef13f6d,
0xbf62bf7bbf228000,0x3f7f3f553e95bec4,0xbf75bf0e3dc93f35,0x3f463e48bef1bf6d,0xbef13e483f463f80,0x3dc9bf0ebf75bf6d,0x3e953f553f7f3f35,0xbf22bf7bbf62bec4,
0x3cc93f2c3f7e3f55,0xbea1bf5cbf7cbf22,0xbf093e163f423f80,0x3e89bedbbf6abf75,0x3f6f3f713efcbe48,0xbf7fbf4ebe603ef1,0x3f133f783f653ec4,0xbf4abf80bf39bdc9,
0xbf80bf3ebdfb3f0e,0x3f733f04be2fbf46,0xbf58bf7dbf278000,0x3f773f673ecfbe95,0xbeb83eac3f5f3f7b,0x3d97bf18bf7abf62,0xbf51be793ee63f6d,0x3f1dbd49bf31bf7f,
0x3e163f463f803f35,0xbeacbf62bf78bf0e,0x3f043f753f673ec4,0xbf2cbf7fbf4ebe48,0xbf183dc93f3e3f80,0x3edbbe95bf5cbf7b,0xbe793ef13f713f6d,0x3d49bf22bf7dbf55,
0xbf7dbf223d493f35,0x3f713ef1be79bf55,0xbf5cbe953edb3f6d,0x3f3e3dc9bf18bf7b,0xbf4ebf7fbf2c8000,0x3f673f753f04be48,0xbf78bf62beac3ec4,0x3f803f463e16bf0e,
0xbdfb3f183f7c3f55,0x3cc9bf2cbf7fbf46,0xbea13edb3f6f3f6d,0x3e60bf04bf77bf62,0xbefc3e793f583f7b,0x3ecfbeacbf65bf75,0xbf273d493f393f80,0x3f13be16bf4abf7f,
0xbf7ebf4ebe2f3f0e,0x3f803f3e3d97bf22,0xbf73bf67beb83ec4,0x3f7a3f5c3e89bef1,0xbf5fbf78bf093e48,0x3f6a3f713ee6be95,0xbf42bf80bf318000,0x3f513f7d3f1dbdc9,
0x3f003f003f003f00,0x3f003f003f003f00,0x3f003f003f003f00,0x3f003f003f003f00,0x3f003f003f003f00,0x3f003f003f003f00,0x3f003f003f003f00,0x3f003f003f003f00,
0xbf003f00bf003f00,0xbf003f00bf003f00,0xbf003f00bf003f00,0xbf003f00bf003f00,0xbf003f00bf003f00,0xbf003f00bf003f00,0xbf003f00bf003f00,0xbf003f00bf003f00,
0x3efc3f043f093f0e,0x3ecf3edb3ee63ef1,0x3f273f2c3f313f35,0x3f133f183f1d3f22,0x3dfb3e163e2f3e48,0x3cc93d493d973dc9,0x3ea13eac3eb83ec4,0x3e603e793e893e95,
0xbf5fbf5cbf58bf55,0xbf6abf67bf65bf62,0xbf42bf3ebf39bf35,0xbf51bf4ebf4abf46,0xbf7ebf7dbf7cbf7b,0xbf80bf80bf7fbf7f,0xbf73bf71bf6fbf6d,0xbf7abf78bf77bf75,
0xbf4ebf46bf3ebf35,0xbf67bf62bf5cbf55,0xbf78bf75bf71bf6d,0xbf80bf7fbf7dbf7b,0xbe16bdc9bd490000,0xbeacbe95be79be48,0xbf04bef1bedbbec4,0xbf2cbf22bf18bf0e,
0xbf18bf22bf2cbf35,0xbedbbef1bf04bf0e,0xbe79be95beacbec4,0xbd49bdc9be16be48,0xbf7dbf7fbf80bf80,0xbf71bf75bf78bf7b,0xbf5cbf62bf67bf6d,0xbf3ebf46bf4ebf55,
0xbeb8bedbbefcbf0e,0xbd97be16be60be95,0xbf51bf5cbf65bf6d,0xbf1dbf2cbf39bf46,0xbf80bf80bf7ebf7b,0xbf73bf78bf7cbf7f,0xbf58bf4ebf42bf35,0xbf77bf71bf6abf62,
0x3f6f3f673f5f3f55,0x3f7f3f7d3f7a3f75,0x3f133f043ee63ec4,0x3f4a3f3e3f313f22,0x3cc9bd49bdfbbe48,0x3ea13e793e2f3dc9,0xbf09bf18bf27bf35,0xbe89beacbecfbef1,
0xbf75bf7bbf7fbf80,0xbf46bf55bf62bf6d,0xbef1bf0ebf22bf35,0xbdc9be48be95bec4,0x3e953e483dc90000,0x3f223f0e3ef13ec4,0x3f623f553f463f35,0x3f7f3f7b3f753f6d,
0x3e953e483dc98000,0x3f223f0e3ef13ec4,0x3f623f553f463f35,0x3f7f3f7b3f753f6d,0x3f753f7b3f7f3f80,0x3f463f553f623f6d,0x3ef13f0e3f223f35,0x3dc93e483e953ec4,
0x3f093edb3ea13e48,0x3f5f3f4e3f393f22,0xbecfbf04bf1dbf35,0x3d97bd49be2fbe95,0x3f133f2c3f423f55,0x3dfb3e793eb83ef1,0x3f803f7d3f773f6d,0x3f653f713f7a3f7f,
0x3f583f673f733f7b,0x3efc3f183f313f46,0x3f6a3f5c3f4a3f35,0x3f7f3f803f7c3f75,0xbf51bf3ebf27bf0e,0xbf7ebf78bf6fbf62,0x3cc93e163e893ec4,0xbee6beacbe60bdc9,
0x3eac3ef13f183f35,0xbe79bdc93d493e48,0xbf3ebf22bf04bec4,0xbf7dbf75bf67bf55,0x3edb3e953e160000,0x3f5c3f463f2c3f0e,0x3f803f7f3f783f6d,0x3f4e3f623f713f7b,
0xbf71bf62bf4ebf35,0xbf78bf7fbf80bf7b,0xbf2cbf46bf5cbf6d,0xbe16be95bedbbf0e,0x3f673f753f7d3f80,0x3f043f223f3e3f55,0xbd493dc93e793ec4,0xbf18bef1beacbe48,
0xbf42bf5cbf6fbf7b,0xbe2fbeacbefcbf22,0xbf4abf2cbf09bec4,0xbf80bf7dbf73bf62,0x3ee63f183f393f55,0xbe60bd493dfb3e95,0x3f773f673f513f35,0x3f6a3f783f7f3f7f,
0x3f273f043eb83e48,0x3f7c3f713f5f3f46,0xbf1dbf3ebf58bf6d,0x3cc9be16bea1bef1,0xbf65bf4ebf31bf0e,0xbf7abf80bf7ebf75,0x3e893edb3f133f35,0xbecfbe79bd973dc9,
0x3f553f6d3f7b3f80,0x3e483ec43f0e3f35,0xbf0ebec4be480000,0xbf7bbf6dbf55bf35,0xbf55bf6dbf7bbf80,0xbe48bec4bf0ebf35,0x3f0e3ec43e480000,0x3f7b3f6d3f553f35,
0xbf0ebec4be488000,0xbf7bbf6dbf55bf35,0xbf55bf6dbf7bbf80,0xbe48bec4bf0ebf35,0x3f0e3ec43e488000,0x3f7b3f6d3f553f35,0x3f553f6d3f7b3f80,0x3e483ec43f0e3f35,
0xbf7fbf7dbf6fbf55,0xbf13bf3ebf5fbf75,0x3dfb3eac3f093f35,0xbf31bf04bea1bdc9,0x3f653f783f803f7b,0x3e603edb3f1d3f46,0x3e893d49be2fbec4,0x3f6a3f4e3f273ef1,
0x3d97be16beb8bf0e,0x3f513f2c3efc3e95,0xbf7ebf71bf58bf35,0xbf39bf5cbf73bf7f,0xbee6be79bcc93e48,0xbf7abf67bf4abf22,0x3f773f803f7c3f6d,0x3ecf3f183f423f62,
0x3f803f753f5c3f35,0x3f183f463f673f7b,0xbeacbdc93e163ec4,0xbf78bf62bf3ebf0e,0xbf2cbef1be790000,0xbf7dbf7fbf71bf55,0xbedbbf22bf4ebf6d,0x3f043e953d49be48,
0x3d493e953f043f35,0xbf4ebf22bedbbe48,0xbf71bf7fbf7dbf6d,0xbe79bef1bf2cbf55,0xbf3ebf62bf78bf80,0x3e16bdc9beacbf0e,0x3f673f463f183ec4,0x3f5c3f753f803f7b,
0xbf7abf80bf73bf55,0xbe89bf04bf39bf62,0x3eb83f183f4a3f6d,0xbf27bedbbe2f3dc9,0x3f133eac3d97be48,0x3f7e3f7d3f6a3f46,0xbf80bf78bf5fbf35,0xbee6bf2cbf58bf75,
0x3e60bd49bea1bf0e,0x3f773f5c3f313ef1,0xbf6fbf4ebf1dbec4,0xbf42bf67bf7cbf7f,0x3f513f713f7f3f7b,0xbdfb3e163ecf3f22,0x3cc9be79befcbf35,0x3f653f3e3f093e95,
0xbf22bf55bf75bf80,0x3ef13e48bdc9bec4,0x3f7f3f7b3f623f35,0x3e953f0e3f463f6d,0xbf46bf0ebe950000,0xbf62bf7bbf7fbf6d,0x3dc9be48bef1bf35,0x3f753f553f223ec4,
0x3f463f0e3e958000,0x3f623f7b3f7f3f6d,0xbdc93e483ef13f35,0xbf75bf55bf22bec4,0xbf22bf55bf75bf80,0x3ef13e48bdc9bec4,0x3f7f3f7b3f623f35,0x3e953f0e3f463f6d,
0x3ecf3f2c3f5f3f7b,0xbf42bf04be603dc9,0x3e2fbe16bee6bf35,0x3f7e3f673f393ef1,0x3f803f713f4a3f0e,0x3ea13f183f513f75,0xbf58bf78bf7fbf6d,0x3e89bd49beb8bf22,
0xbf6abf3ebefcbe48,0xbf27bf5cbf7abf7f,0x3f7c3f7d3f653f35,0x3dfb3edb3f313f62,0x3cc93eac3f1d3f55,0xbf73bf4ebf13be95,0x3f093e79bd97bec4,0x3f773f803f6f3f46,
0x3e79bdc9bedbbf35,0x3f803f753f4e3f0e,0x3e163ef13f3e3f6d,0xbf71bf46bf04be48,0x3f5c3f223eac0000,0x3f2c3f623f7d3f7b,0xbf18be953d493ec4,0xbf67bf7fbf78bf55,
0x3f783f7f3f673f35,0xbd493e953f183f55,0xbf7dbf62bf2cbec4,0xbeacbf22bf5cbf7b,0x3f043f463f713f80,0xbf3ebef1be163e48,0xbf4ebf75bf80bf6d,0x3edb3dc9be79bf0e,
0xbf77bf4ebf09be48,0xbeb8bf2cbf65bf7f,0x3f7f3f673f313ec4,0x3e2f3f043f4a3f75,0xbf7ebf78bf51bf0e,0x3cc9beacbf27bf62,0x3f733f803f6a3f35,0xbe603e163efc3f46,
0xbe89bf18bf58bf7b,0x3f6f3f3e3ee63dc9,0x3d973edb3f393f6d,0xbf7cbf5cbf1dbe95,0x3dfbbe79bf13bf55,0x3f803f713f423ef1,0xbea13d493ecf3f35,0xbf7abf7dbf5fbf22,
0x3ec43f353f6d3f80,0xbf6dbf35bec40000,0xbec4bf35bf6dbf80,0x3f6d3f353ec40000,0x3ec43f353f6d3f80,0xbf6dbf35bec40000,0xbec4bf35bf6dbf80,0x3f6d3f353ec40000,
0xbf6dbf35bec48000,0xbec4bf35bf6dbf80,0x3f6d3f353ec48000,0x3ec43f353f6d3f80,0xbf6dbf35bec48000,0xbec4bf35bf6dbf80,0x3f6d3f353ec48000,0x3ec43f353f6d3f80,
0x3f1d3e79be2fbf0e,0x3f393f713f7f3f62,0xbee6bd493eb83f35,0xbf58bf7dbf77bf46,0x3f5f3f183e60be48,0x3ecf3f3e3f733f7f,0xbf42bedbbcc93ec4,0xbf13bf5cbf7ebf75,
0x3f4a3f783f7c3f55,0xbf31beac3d973ef1,0xbf65bf80bf6fbf35,0x3f093e16be89bf22,0x3efc3f4e3f7a3f7b,0xbf6abf2cbea13dc9,0xbf27bf67bf80bf6d,0x3f513f043dfbbe95,
0xbf5cbf7fbf71bf35,0x3f2c3e95be16bf0e,0x3f183f623f803f6d,0xbf67bf22be793e48,0xbf78bf46bedb0000,0xbd49bef1bf4ebf7b,0x3f7d3f753f3e3ec4,0xbeac3dc93f043f55,
0x3f043dc9beacbf35,0x3f3e3f753f7d3f55,0xbf4ebef1bd493ec4,0xbedbbf46bf78bf7b,0xbe79bf22bf67bf80,0x3f803f623f183e48,0xbe163e953f2c3f6d,0xbf71bf7fbf5cbf0e,
0xbf39beac3dfb3f0e,0xbee6bf4ebf7cbf75,0x3e60be79bf27bf6d,0x3f5f3f803f6a3f22,0x3eb83f3e3f773f7b,0xbf7fbf5cbf09bdc9,0xbf51bf7dbf73bf35,0x3f4a3edbbcc9bef1,
0xbf31bf71bf7ebf55,0x3f653f183e2fbe95,0x3f7a3f783f423ec4,0xbefcbd493ecf3f46,0xbf6fbf2cbe893e48,0xbd97bf04bf58bf7f,0x3f133e16bea1bf35,0x3f1d3f673f803f62,
0xbdc9bf0ebf62bf80,0x3f753f7b3f463ec4,0xbf22be483e953f35,0xbef1bf55bf7fbf6d,0x3f7f3f553ef10000,0xbe953e483f223f6d,0xbf46bf7bbf75bf35,0x3f623f0e3dc9bec4,
0x3f7f3f553ef18000,0xbe953e483f223f6d,0xbf46bf7bbf75bf35,0x3f623f0e3dc9bec4,0x3dc93f0e3f623f80,0xbf75bf7bbf46bec4,0x3f223e48be95bf35,0x3ef13f553f7f3f6d,
0xbf7cbf71bf27be48,0x3f1d3e16beb8bf46,0x3f313e79be89bf35,0x3ea13f3e3f7a3f75,0x3f093d49bee6bf55,0x3efc3f5c3f803f62,0x3ecf3f4e3f7e3f6d,0xbf7fbf67bf13bdc9,
0x3e2fbeacbf42bf7b,0x3f4a3f7d3f6f3f22,0x3f393f783f773f35,0xbf73bf2cbe603e95,0x3f583f803f653f0e,0xbf5fbf04bcc93ef1,0xbf6abf18bdfb3ec4,0x3d97bedbbf51bf7f,
0xbf3ebe953e793f35,0xbe16bf22bf71bf7b,0x3f673f7f3f4e3ec4,0xbf5cbef13d493f0e,0x3f803f623f040000,0xbf18bdc93edb3f55,0xbeacbf46bf7dbf6d,0x3f783f753f2c3e48,
0xbf2cbf75bf78bf35,0x3f7d3f463eacbe48,0xbedb3dc93f183f6d,0xbf04bf62bf80bf55,0xbd493ef13f5c3f80,0xbf4ebf7fbf67bf0e,0x3f713f223e16bec4,0xbe793e953f3e3f7b,
0xbea13e793f393f7b,0xbf09bf67bf7ebf46,0xbf5fbf80bf51bec4,0x3f6f3f183d97bef1,0x3f273e16becfbf55,0x3e2f3f2c3f773f75,0x3f1d3f713f7a3f35,0xbf80bf5cbee63dc9,
0xbf73bf78bf31be48,0x3f583edbbdfbbf22,0x3efcbd49bf13bf6d,0x3eb83f4e3f7f3f62,0x3f423f7d3f6a3f0e,0xbf7cbf3ebe893e95,0xbf4abeac3e603f35,0x3cc9bf04bf65bf7f,
0xbe483ec43f553f80,0xbf0ebf6dbf7bbf35,0x3f7b3f6d3f0e0000,0xbf55bec43e483f35,0x3e48bec4bf55bf80,0x3f0e3f6d3f7b3f35,0xbf7bbf6dbf0e0000,0x3f553ec4be48bf35,
0xbf7bbf6dbf0e8000,0x3f553ec4be48bf35,0xbe483ec43f553f80,0xbf0ebf6dbf7bbf35,0x3f7b3f6d3f0e8000,0xbf55bec43e483f35,0x3e48bec4bf55bf80,0x3f0e3f6d3f7b3f35,
0x3ea13f4e3f803f55,0xbf58bf80bf4abe95,0xbf5fbedb3e2f3f35,0x3eb8be79bf42bf7f,0x3d97bf04bf6abf7b,0x3f133f713f773f22,0x3f7e3f3e3e60bec4,0xbf31be163ee63f62,
0xbf73bf18bcc93f0e,0x3f09bd49bf1dbf75,0xbefcbf67bf7cbf35,0x3f6f3f783f273dc9,0x3f7f3f5c3ecfbe48,0xbf51beac3e893f46,0x3dfb3f2c3f7a3f6d,0xbf39bf7dbf65bef1,
0x3edb3f623f7d3f35,0xbf5cbf7fbf3ebe48,0x3f803f463e79bec4,0xbf4ebe953eac3f55,0xbf71bf75bf180000,0x3f783f223d49bf0e,0xbf2cbdc93f043f6d,0x3e16bef1bf67bf7b,
0xbf67bef13e163f35,0x3f04bdc9bf2cbf7b,0x3d493f223f783f6d,0xbf18bf75bf71bf0e,0x3eacbe95bf4ebf80,0x3e793f463f803f55,0xbf3ebf7fbf5cbec4,0x3f7d3f623edbbe48,
0x3e2f3f3e3f7f3f55,0xbf1dbf78bf6abef1,0xbf39be163efc3f6d,0x3ea1beacbf58bf7f,0xbf7abf67bee63e48,0x3f773f18bcc9bf22,0xbeb8bf5cbf7ebf35,0x3f423f803f513e95,
0xbf7cbf2cbd973f0e,0x3f4a3e79becfbf62,0xbf31bf7dbf5fbec4,0x3f733f713f09bdc9,0x3e60bedbbf65bf7b,0x3e893f4e3f803f46,0x3f6f3f04bdfbbf35,0xbf27bd493f133f75,
0x3ef1be48bf46bf80,0xbdc93f0e3f753f6d,0xbe95bf55bf7fbf35,0x3f223f7b3f623ec4,0xbf62bf7bbf220000,0x3f7f3f553e95bec4,0xbf75bf0e3dc93f35,0x3f463e48bef1bf6d,
0x3f623f7b3f228000,0xbf7fbf55be953ec4,0x3f753f0ebdc9bf35,0xbf46be483ef13f6d,0x3ef1be48bf46bf80,0xbdc93f0e3f753f6d,0xbe95bf55bf7fbf35,0x3f223f7b3f623ec4,
0x3f313d49bf1dbf7b,0xbee63e793f513f7f,0x3f7a3f18bd97bf35,0xbf5fbeac3eb83f62,0xbecfbf67bf77bf0e,0x3f273f7d3f583e95,0x3e2fbf04bf73bf6d,0x3dfb3f3e3f803f46,
0x3f393f803f4a3e48,0xbf65bf78bf133dc9,0x3e603f4e3f7f3f35,0xbefcbf71bf6fbef1,0x3f6a3edbbe89bf55,0xbf42be163f093f75,0x3f7c3f5c3ea1bec4,0xbf7ebf2cbcc93f22,
0x3f7d3f22bd49bf35,0xbf71bef13e793f55,0x3f5c3e95bedbbf6d,0xbf3ebdc93f183f7b,0x3f4e3f7f3f2c0000,0xbf67bf75bf043e48,0x3f783f623eacbec4,0xbf80bf46be163f0e,
0x3e163f463f803f35,0xbeacbf62bf78bf0e,0x3f043f753f673ec4,0xbf2cbf7fbf4ebe48,0xbf183dc93f3e3f80,0x3edbbe95bf5cbf7b,0xbe793ef13f713f6d,0x3d49bf22bf7dbf55,
0x3f1d3f7d3f513e48,0xbf31bf80bf42bdc9,0x3ee63f713f6a3ec4,0xbf09bf78bf5fbe95,0x3e893f5c3f7a3f0e,0xbeb8bf67bf73bef1,0x3d973f3e3f803f35,0xbe2fbf4ebf7ebf22,
0xbf4abe163f133f7b,0x3f393d49bf27bf7f,0xbf65beac3ecf3f6d,0x3f583e79befcbf75,0xbf77bf043e603f55,0x3f6f3edbbea1bf62,0xbf7fbf2c3cc93f35,0x3f7c3f18bdfbbf46,
0xbf8000003f80,0xbf8000003f80,0xbf8000003f80,0xbf8000003f80,0xbf8000003f80,0xbf8000003f80,0xbf8000003f80,0xbf8000003f80,
0x3f808000bf808000,0x3f808000bf808000,0x3f808000bf808000,0x3f808000bf808000,0x3f808000bf808000,0x3f808000bf808000,0x3f808000bf808000,0x3f808000bf808000,
0x3e89bf78be603f7b,0x3eb8bf71bea13f75,0x3d97bf80bcc93f80,0x3e2fbf7dbdfb3f7f,0x3f1dbf4ebf133f55,0x3f31bf3ebf273f46,0x3ee6bf67becf3f6d,0x3f09bf5cbefc3f62,
0x3f773e79bf7abe48,0x3f6f3eacbf73be95,0x3f7f3d49bf808000,0x3f7c3e16bf7ebdc9,0x3f4a3f18bf51bf0e,0x3f393f2cbf42bf22,0x3f653edbbf6abec4,0x3f583f04bf5fbef1,
0x3f4ebf22bf3e3f35,0x3f67bef1bf5c3f0e,0x3f78be95bf713ec4,0x3f80bdc9bf7d3e48,0x3e16bf7fbd493f80,0x3eacbf75be793f7b,0x3f04bf62bedb3f6d,0x3f2cbf46bf183f55,
0x3f183f46bf2cbf35,0x3edb3f62bf04bf55,0x3e793f75beacbf6d,0x3d493f7fbe16bf7b,0x3f7d3dc9bf808000,0x3f713e95bf78be48,0x3f5c3ef1bf67bec4,0x3f3e3f22bf4ebf0e,
0x3f6a3eacbf77be48,0x3f423f18bf58bef1,0x3f7cbe79bf733ec4,0x3f7e3d49bf803dc9,0x3f39bf3ebf1d3f55,0x3f65bf04bf513f22,0x3e60bf7dbd973f80,0x3efcbf67beb83f75,
0xbecf3f713e89bf7b,0xbf273f4e3f09bf62,0x3e2f3f78bea1bf6d,0xbdfb3f80bcc9bf7f,0x3f313f2cbf4abf0e,0x3ee63f5cbf13bf46,0x3f7a3e16bf7f8000,0x3f5f3edbbf6fbe95,
0x3e95bf7bbdc93f80,0x3f22bf55bef13f6d,0x3f62bf0ebf463f35,0x3f7fbe48bf753ec4,0x3f753e48bf7f0000,0x3f463f0ebf62bec4,0x3ef13f55bf22bf35,0x3dc93f7bbe95bf6d,
0x3f753e48bf7f8000,0x3f463f0ebf62bec4,0x3ef13f55bf22bf35,0x3dc93f7bbe95bf6d,0xbe953f7b3dc9bf80,0xbf223f553ef1bf6d,0xbf623f0e3f46bf35,0xbf7f3e483f75bec4,
0x3f7abeacbf653f0e,0x3f773e16bf803dc9,0x3eb8bf78bdfb3f80,0x3f42bf3ebf133f62,0xbe2f3f80bd97bf7b,0xbf1d3f5c3ecfbf75,0x3f393f18bf5fbec4,0x3ea13f67bf09bf46,
0x3e603f71bee6bf55,0xbe893f7d3cc9bf7f,0x3f6f3e79bf7e8000,0x3f273f2cbf51bef1,0xbf7cbd493f7fbe48,0xbf4abf043f6a3e95,0xbf313f4e3efcbf6d,0xbf733edb3f58bf22,
0x3eac3f62bf18bf35,0xbe793f7fbd49bf7b,0xbf3e3f463f04bf6d,0xbf7d3e953f67bf0e,0x3edbbf75be163f80,0x3f5cbf22bf2c3f55,0x3f80bdc9bf783ec4,0x3f4e3ef1bf71be48,
0xbf713ef13f4ebf35,0xbf78bdc93f80be48,0xbf2cbf223f5c3ec4,0xbe16bf753edb3f55,0x3f673e95bf7d8000,0x3f043f46bf3ebf0e,0xbd493f7fbe79bf6d,0xbf183f623eacbf7b,
0xbf7f3e793f6abf0e,0xbf51bedb3f773dc9,0xbdfb3f80be60bf6d,0xbf393f4e3ee6bf75,0x3f733e16bf803e48,0x3f093f3ebf4abef1,0x3efcbf71be2f3f80,0x3f6fbf04bf423f46,
0xbd97bf783ecf3f55,0x3f13bf67be893f7f,0xbf7e3d493f7abec4,0xbf31bf183f653e95,0xbea13f7dbcc9bf7b,0xbf583f2c3f1dbf62,0x3f5f3eacbf7c8000,0x3eb83f5cbf27bf22,
0x3f0ebf6dbe483f80,0x3f7bbec4bf553f35,0x3f553ec4bf7b0000,0x3e483f6dbf0ebf35,0xbf0e3f6d3e48bf80,0xbf7b3ec43f55bf35,0xbf55bec43f7b0000,0xbe48bf6d3f0e3f35,
0x3f553ec4bf7b8000,0x3e483f6dbf0ebf35,0xbf0e3f6d3e48bf80,0xbf7b3ec43f55bf35,0xbf55bec43f7b8000,0xbe48bf6d3f0e3f35,0x3f0ebf6dbe483f80,0x3f7bbec4bf553f35,
0x3f273f18bf6abe48,0xbe2f3f80be89bf62,0x3f1dbf67be603f80,0x3f80be79bf653f22,0xbea1bf5c3f313f0e,0x3f09bf71bdfb3f7f,0xbf5f3f2c3f13bf6d,0xbf6fbe163f7fbe95,
0xbf423f4e3ecfbf7b,0xbf7c3d493f77bef1,0x3f4a3edbbf7a8000,0x3cc93f78bee6bf46,0x3f73bf04bf393f55,0x3f583eacbf7e3dc9,0xbefcbf3e3f513ec4,0x3eb8bf7d3d973f75,
0xbf803e953f5cbf35,0xbf18bf223f673e48,0x3eacbf7f3e163f6d,0x3f78bef1bf3e3f55,0x3f2cbf62be793f80,0x3f7dbdc9bf713f0e,0x3edb3f46bf4ebec4,0xbf043f753d49bf7b,
0xbd49bf753f043f35,0x3f4ebf46bedb3f7b,0x3f713dc9bf7d3ec4,0x3e793f62bf2cbf0e,0x3f3e3ef1bf788000,0xbe163f7fbeacbf55,0xbf673f223f18bf6d,0xbf5cbe953f80be48,
0x3f58bf3ebee63f7b,0x3f5f3e79bf803e95,0xbf6abe163f7ebec4,0xbd97bf713f133f22,0x3e2f3f67bf27bf0e,0xbf4a3f4e3eb8bf7f,0x3f39bf5cbe893f80,0x3f733d49bf7a3ef1,
0x3f093f2cbf65be48,0xbefc3f78bcc9bf75,0x3ecfbf7d3dfb3f6d,0x3f7fbeacbf513f46,0xbf7c3edb3f42bf55,0xbf1dbf183f6f3dc9,0x3f313f04bf778000,0xbea13f80be60bf62,
0x3f46bf55be953f80,0x3f623e48bf7f3ec4,0xbdc93f7bbef1bf35,0xbf753f0e3f22bf6d,0xbf22bf0e3f750000,0x3ef1bf7b3dc93f6d,0x3f7fbe48bf623f35,0x3e953f55bf46bec4,
0x3f223f0ebf758000,0xbef13f7bbdc9bf6d,0xbf7f3e483f62bf35,0xbe95bf553f463ec4,0x3f46bf55be953f80,0x3f623e48bf7f3ec4,0xbdc93f7bbef1bf35,0xbf753f0e3f22bf6d,
0xbeb83f80be89bf55,0xbf7f3e793f58bf46,0x3f51bf4ebea13f80,0x3f4a3eacbf803e95,0x3f393edbbf7e3e48,0xbee63f7dbe2fbf62,0xbe60bf5c3f423ec4,0x3f5fbf3ebecf3f7f,
0xbf6fbd493f77bf0e,0x3d97bf783f093f22,0x3f133f18bf738000,0xbf1d3f713cc9bf75,0xbf313f673dfbbf7b,0xbf65be163f7cbef1,0x3f7abf04bf273f6d,0x3efc3f2cbf6abdc9,
0x3e79bf7f3edb3f35,0x3f80be95bf4e3f55,0x3e163f62bf3ebec4,0xbf713f223f04bf7b,0x3f5cbf46beac3f80,0x3f2c3ef1bf7d3e48,0xbf183f75bd49bf6d,0xbf67bdc93f78bf0e,
0x3f78bdc9bf673f35,0xbd493f75bf18bf0e,0xbf7d3ef13f2cbf6d,0xbeacbf463f5c3e48,0x3f043f22bf718000,0xbf3e3f623e16bf7b,0xbf4ebe953f80bec4,0x3edbbf7f3e793f55,
0xbefc3f7dbe60bf55,0xbf6abd493f73bf22,0x3f27bf713cc93f6d,0x3f513e79bf7e3ef1,0xbf4a3f5c3e2fbf7b,0xbf31bedb3f7fbe95,0x3f65bf3ebeb83f80,0x3f093f18bf773dc9,
0xbf5fbe163f7abf0e,0x3ecfbf803ea13f46,0x3f423eacbf803ec4,0xbf133f78bdfbbf62,0xbf1dbf043f7cbe48,0x3f39bf67bd973f75,0x3ee63f2cbf6f8000,0xbf583f4e3e89bf7f,
0x3f6dbf35bec43f80,0x3ec43f35bf6d0000,0xbf6d3f353ec4bf80,0xbec4bf353f6d0000,0x3f6dbf35bec43f80,0x3ec43f35bf6d0000,0xbf6d3f353ec4bf80,0xbec4bf353f6d0000,
0x3ec43f35bf6d8000,0xbf6d3f353ec4bf80,0xbec4bf353f6d8000,0x3f6dbf35bec43f80,0x3ec43f35bf6d8000,0xbf6d3f353ec4bf80,0xbec4bf353f6d8000,0x3f6dbf35bec43f80,
0xbf7e3f043f13bf7b,0xbcc9bf673f423e95,0x3f73bf2cbecf3f80,0x3e603f4ebf5fbdc9,0xbf773e163f58bf55,0x3eb8bf803ee63f22,0x3f7fbeacbf393f6d,0xbe2f3f78bf1dbef1,
0xbdfbbf5c3f513e48,0x3f80bedbbf273f75,0x3ea13f3ebf6a8000,0xbf7a3f183efcbf7f,0x3e89bf7d3f093f0e,0x3f6fbd49bf653f46,0xbd973f71bf31bec4,0xbf7c3e793f4abf62,
0x3f5c3dc9bf713f35,0xbf2c3f75be16bf55,0xbf18bef13f80bec4,0x3f67bf46be793f7b,0x3f78bf22bedb3f80,0x3d493f62bf4ebe48,0xbf7d3e953f3ebf6d,0x3eacbf7f3f043f0e,
0xbf043f7fbeacbf35,0xbf3ebe953f7dbf0e,0x3f4ebf62bd493f6d,0x3edb3f22bf783e48,0x3e793f46bf678000,0xbf803ef13f18bf7b,0x3e16bf753f2c3ec4,0x3f71bdc9bf5c3f55,
0x3cc9bf673f4a3e48,0x3f73be16bf513f62,0x3f093f04bf7f3ec4,0xbf773f2c3eb8bf7f,0xbf6a3d493f5fbf55,0x3f27bf783e603f46,0x3f7cbf18bee63f80,0xbdfb3f71bf39be95,
0x3f80bedbbf1d3f7b,0xbea13f7dbf13bef1,0xbf583f5c3d97bf6d,0xbe89bf3e3f6fbdc9,0x3ecfbf803efc3f0e,0x3f423e79bf7a3f22,0x3e2f3f4ebf658000,0xbf7e3eac3f31bf75,
0x3f7fbf0ebef13f80,0xbe953f7bbf22bec4,0xbf46be483f75bf35,0x3f62bf55bdc93f6d,0x3dc93f55bf620000,0xbf753e483f46bf6d,0x3f22bf7b3e953f35,0x3ef13f0ebf7f3ec4,
0x3dc93f55bf628000,0xbf753e483f46bf6d,0x3f22bf7b3e953f35,0x3ef13f0ebf7f3ec4,0xbf7f3f0e3ef1bf80,0x3e95bf7b3f223ec4,0x3f463e48bf753f35,0xbf623f553dc9bf6d,
0xbf13bedb3f7fbf0e,0x3f7ebf18becf3f7f,0x3f80bf04befc3f80,0xbee63f80bf09bef1,0x3f7abf2cbea13f7b,0xbe893f78bf31be95,0xbeb83f7dbf1dbec4,0xbf27beac3f7cbf22,
0x3f51bf673d973f55,0x3dfb3f4ebf6a3dc9,0x3cc93f5cbf5f8000,0xbf653d493f58bf62,0x3e603f3ebf733e48,0xbf773e793f39bf75,0xbf6f3e163f4abf6d,0x3f42bf713e2f3f46,
0xbf3e3f75be79bf35,0xbe16bf463f71be48,0x3f67bdc9bf4e3f6d,0xbf5c3f62bd49bf55,0x3f80bef1bf043f80,0xbf183f7fbedbbf0e,0xbeacbf223f7dbec4,0x3f78be95bf2c3f7b,
0xbf2cbe953f78bf35,0x3f7dbf22beac3f7b,0xbedb3f7fbf18bec4,0xbf04bef13f80bf0e,0xbd493f62bf5c8000,0xbf4ebdc93f67bf55,0x3f71bf46be163f6d,0xbe793f75bf3ebe48,
0x3ee63f04bf803f0e,0xbf7a3eac3f1dbf7f,0xbf773f3e3e2fbf6d,0x3ecfbf7d3f273e95,0xbd97bf4e3f6fbe48,0x3f513d49bf5f3f62,0x3f7ebedbbf093f80,0xbf393f78bea1bf22,
0xbf653f5cbcc9bf55,0x3e60bf713f4a3dc9,0xbe89bf2c3f7cbec4,0x3f6abe16bf423f75,0x3f7fbf18beb83f7b,0xbf133f80befcbef1,0xbdfb3f67bf588000,0xbf31be793f73bf46,
0x3f7bbec4bf0e3f80,0xbf553f6dbe48bf35,0x3e48bf6d3f550000,0x3f0e3ec4bf7b3f35,0xbf7b3ec43f0ebf80,0x3f55bf6d3e483f35,0xbe483f6dbf550000,0xbf0ebec43f7bbf35,
0xbe483f6dbf558000,0xbf0ebec43f7bbf35,0x3f7bbec4bf0e3f80,0xbf553f6dbe48bf35,0x3e48bf6d3f558000,0x3f0e3ec4bf7b3f35,0xbf7b3ec43f0ebf80,0x3f55bf6d3e483f35,
0x3ee6bf7d3f313e48,0x3e603f2cbf7e3ef1,0x3f77beacbf133f80,0xbf6a3f5cbd97bf46,0xbf423f78beb8bf0e,0x3e2fbf673f5fbdc9,0xbf4abd493f58bf6d,0x3f80bf18bea13f75,
0x3f65be16bf393f7b,0xbf7a3f3e3dfbbf62,0xbe893f71bf518000,0xbecfbf043f7fbf22,0xbf27be793f6fbf55,0x3f7cbedbbefc3f7f,0x3f1dbf803f093ec4,0x3cc93f4ebf733e95,
0xbedbbef13f7dbf35,0x3f5cbdc9bf3e3f7b,0xbf803f223e79bf6d,0x3f4ebf753eac3f0e,0x3f71be95bf183f80,0xbf783f463d49bf55,0x3f2cbf7f3f043ec4,0xbe163f62bf673e48,
0x3f67bf623e163f35,0xbf043f7fbf2cbe48,0xbd49bf463f78bec4,0x3f183e95bf713f55,0xbeac3f75bf4e8000,0xbe79bf223f80bf0e,0x3f3e3dc9bf5c3f6d,0xbf7d3ef13edbbf7b,
0xbf513d493f42bf7b,0x3f7ebf04beb83f75,0x3cc9bf4e3f77bec4,0x3ee63edbbf7a3f46,0x3f58bf713ea13f0e,0xbefc3f7dbf39bdc9,0x3f6abe79bf1d3f80,0xbf7f3f2c3e2fbf62,
0x3f13bf803f273e48,0xbdfb3f5cbf6f3e95,0x3f80bf18be893f6d,0xbf653f67be60bf22,0x3f093eacbf733f55,0xbf5f3e163f31bf7f,0xbecf3f78bf4a8000,0xbd97bf3e3f7cbef1,
0x3f62be48bf223f80,0xbf7f3f0e3e95bf6d,0x3f75bf553dc93f35,0xbf463f7bbef1bec4,0x3ef1bf7b3f460000,0xbdc93f55bf753ec4,0xbe95bf0e3f7fbf35,0x3f223e48bf623f6d,
0xbef13f7bbf468000,0x3dc9bf553f75bec4,0x3e953f0ebf7f3f35,0xbf22be483f62bf6d,0x3f62be48bf223f80,0xbf7f3f0e3e95bf6d,0x3f75bf553dc93f35,0xbf463f7bbef1bec4,
0x3f80bf2cbdfb3f55,0xbf733f5cbe2fbf22,0x3f58be16bf273f80,0xbf773edb3ecfbf75,0x3eb8bf713f5fbe48,0xbd973f4ebf7a3ef1,0x3f51bf783ee63ec4,0xbf1d3f80bf31bdc9,
0x3cc93f3ebf7e3f0e,0xbea1bf043f7cbf46,0xbf093f7dbf428000,0x3e89bf673f6abe95,0x3f6fbeacbefc3f7b,0xbf7f3f183e60bf62,0x3f133e79bf653f6d,0xbf4a3d493f39bf7f,
0x3f7dbf463d493f35,0xbf713f62be79bf0e,0x3f5cbf753edb3ec4,0xbf3e3f7fbf18be48,0x3f4ebdc9bf2c3f80,0xbf673e953f04bf7b,0x3f78bef1beac3f6d,0xbf803f223e16bf55,
0x3e163f22bf803f35,0xbeacbef13f78bf55,0x3f043e95bf673f6d,0xbf2cbdc93f4ebf7b,0xbf183f7fbf3e8000,0x3edbbf753f5cbe48,0xbe793f62bf713ec4,0x3d49bf463f7dbf0e,
0x3f7ebf18be2f3f55,0xbf803f2c3d97bf46,0x3f73bedbbeb83f6d,0xbf7a3f043e89bf62,0x3f5fbe79bf093f7b,0xbf6a3eac3ee6bf75,0x3f42bd49bf313f80,0xbf513e163f1dbf7f,
0xbdfb3f4ebf7c3f0e,0x3cc9bf3e3f7fbf22,0xbea13f67bf6f3ec4,0x3e60bf5c3f77bef1,0xbefc3f78bf583e48,0x3ecfbf713f65be95,0xbf273f80bf398000,0x3f13bf7d3f4abdc9,
0xbf8000003f80,0xbf8000003f80,0xbf8000003f80,0xbf8000003f80,0xbf8000003f80,0xbf8000003f80,0xbf8000003f80,0xbf8000003f80,
0x3f808000bf808000,0x3f808000bf808000,0x3f808000bf808000,0x3f808000bf808000,0x3f808000bf808000,0x3f808000bf808000,0x3f808000bf808000,0x3f808000bf808000,
0x3f5fbf04bf583f0e,0x3f6abedbbf653ef1,0x3f42bf2cbf393f35,0x3f51bf18bf4a3f22,0x3f7ebe16bf7c3e48,0x3f80bd49bf7f3dc9,0x3f73beacbf6f3ec4,0x3f7abe79bf773e95,
0x3efc3f5cbf09bf55,0x3ecf3f67bee6bf62,0x3f273f3ebf31bf35,0x3f133f4ebf1dbf46,0x3dfb3f7dbe2fbf7b,0x3cc93f80bd97bf7f,0x3ea13f71beb8bf6d,0x3e603f78be89bf75,
0x3f183f46bf2cbf35,0x3edb3f62bf04bf55,0x3e793f75beacbf6d,0x3d493f7fbe16bf7b,0x3f7d3dc9bf800000,0x3f713e95bf78be48,0x3f5c3ef1bf67bec4,0x3f3e3f22bf4ebf0e,
0xbf4e3f223f3ebf35,0xbf673ef13f5cbf0e,0xbf783e953f71bec4,0xbf803dc93f7dbe48,0xbe163f7f3d49bf80,0xbeac3f753e79bf7b,0xbf043f623edbbf6d,0xbf2c3f463f18bf55,
0xbf6f3edb3f5fbf0e,0xbf7f3e163f7abe95,0xbf133f5c3ee6bf6d,0xbf4a3f2c3f31bf46,0xbcc93f80bdfbbf7b,0xbea13f783e2fbf7f,0x3f093f4ebf27bf35,0x3e893f71becfbf62,
0xbeb8bf673efc3f55,0xbd97bf7d3e603f75,0xbf51bf043f653ec4,0xbf1dbf3e3f393f22,0xbf803d493f7ebe48,0xbf73be793f7c3dc9,0xbf583f183f42bf35,0xbf773eac3f6abef1,
0xbe953f7b3dc9bf80,0xbf223f553ef1bf6d,0xbf623f0e3f46bf35,0xbf7f3e483f75bec4,0xbf75be483f7f0000,0xbf46bf0e3f623ec4,0xbef1bf553f223f35,0xbdc9bf7b3e953f6d,
0xbf75be483f7f8000,0xbf46bf0e3f623ec4,0xbef1bf553f223f35,0xbdc9bf7b3e953f6d,0x3e95bf7bbdc93f80,0x3f22bf55bef13f6d,0x3f62bf0ebf463f35,0x3f7fbe48bf753ec4,
0xbf58bedb3f733e48,0xbefcbf4e3f313f22,0xbf6a3f043f4abf35,0xbf7f3d493f7cbe95,0x3f51bf2cbf273f55,0x3f7ebe79bf6f3ef1,0xbcc9bf7d3e893f6d,0x3ee6bf71be603f7f,
0x3f09bf67bea13f7b,0x3f5fbf18bf393f46,0xbecfbf5c3f1d3f35,0x3d97bf803e2f3f75,0x3f133f3ebf42bf0e,0x3dfb3f78beb8bf62,0x3f80be16bf773ec4,0x3f653eacbf7abdc9,
0x3f71bef1bf4e3f35,0x3f783dc9bf803e48,0x3f2c3f22bf5cbec4,0x3e163f75bedbbf55,0xbf67be953f7d0000,0xbf04bf463f3e3f0e,0x3d49bf7f3e793f6d,0x3f18bf62beac3f7b,
0x3eac3f62bf18bf35,0xbe793f7fbd49bf7b,0xbf3e3f463f04bf6d,0xbf7d3e953f67bf0e,0x3edbbf75be163f80,0x3f5cbf22bf2c3f55,0x3f80bdc9bf783ec4,0x3f4e3ef1bf71be48,
0xbf273f5c3eb8bf7b,0xbf7c3eac3f5fbf22,0x3f1d3f2cbf58bec4,0xbcc93f7dbea1bf62,0x3f65bf18bf313f55,0x3f7a3d49bf7e3e95,0xbe89bf673f133f35,0x3ecfbf78bd973f7f,
0xbf42bf043f6f3e48,0xbe2fbf713efc3f46,0xbf4a3f3e3f09bf6d,0xbf803e163f73bef1,0x3ee63f4ebf39bf0e,0xbe603f80bdfbbf75,0x3f77bedbbf513f35,0x3f6a3e79bf7f3dc9,
0x3f0ebf6dbe483f80,0x3f7bbec4bf553f35,0x3f553ec4bf7b0000,0x3e483f6dbf0ebf35,0xbf0e3f6d3e48bf80,0xbf7b3ec43f55bf35,0xbf55bec43f7b0000,0xbe48bf6d3f0e3f35,
0x3f553ec4bf7b8000,0x3e483f6dbf0ebf35,0xbf0e3f6d3e48bf80,0xbf7b3ec43f55bf35,0xbf55bec43f7b8000,0xbe48bf6d3f0e3f35,0x3f0ebf6dbe483f80,0x3f7bbec4bf553f35,
0xbd973f7dbeb8bf55,0xbf513f3e3efcbf75,0x3f7ebeacbf583f35,0x3f393f04bf73bdc9,0x3ee6bf78bcc93f7b,0x3f7abedbbf4a3f46,0xbf77bd493f7cbec4,0xbecfbf4e3f423ef1,
0xbf7f3e163f6fbf0e,0xbf13bf2c3f5f3e95,0x3dfb3f71bf09bf35,0xbf313f5c3ea1bf7f,0x3f653e79bf803e48,0x3e603f67bf1dbf22,0x3e89bf803e2f3f6d,0x3f6abf18bf273f62,
0xbd49bf753f043f35,0x3f4ebf46bedb3f7b,0x3f713dc9bf7d3ec4,0x3e793f62bf2cbf0e,0x3f3e3ef1bf780000,0xbe163f7fbeacbf55,0xbf673f223f18bf6d,0xbf5cbe953f80be48,
0x3f80be95bf5c3f35,0x3f183f22bf67be48,0xbeac3f7fbe16bf6d,0xbf783ef13f3ebf55,0xbf2c3f623e79bf80,0xbf7d3dc93f71bf0e,0xbedbbf463f4e3ec4,0x3f04bf75bd493f7b,
0xbe603f80bea1bf55,0xbf773f043f31bf62,0x3f6fbf18bf1d3f6d,0x3f423edbbf7c3dc9,0xbf51beac3f7fbe48,0x3dfbbf7d3ecf3f46,0xbcc93f78befcbf35,0xbf653f2c3f09bf75,
0xbf7a3d493f73bf0e,0xbe89bf5c3f393ef1,0x3eb83f4ebf4abec4,0xbf273f673e2fbf7f,0x3f13bf71bd973f7b,0x3f7ebe16bf6a3f22,0xbf803e793f5fbf35,0xbee6bf3e3f583e95,
0xbf463f553e95bf80,0xbf62be483f7fbec4,0x3dc9bf7b3ef13f35,0x3f75bf0ebf223f6d,0x3f223f0ebf750000,0xbef13f7bbdc9bf6d,0xbf7f3e483f62bf35,0xbe95bf553f463ec4,
0xbf22bf0e3f758000,0x3ef1bf7b3dc93f6d,0x3f7fbe48bf623f35,0x3e953f55bf46bec4,0xbf463f553e95bf80,0xbf62be483f7fbec4,0x3dc9bf7b3ef13f35,0x3f75bf0ebf223f6d,
0x3f6abf2cbefc3f7b,0x3f273f04bf7a3dc9,0xbf7c3e163f65bf35,0xbdfbbf673f313ef1,0xbcc9bf713f1d3f0e,0x3f73bf18bf133f75,0xbf093f78bd97bf6d,0xbf773d493f6fbf22,
0x3ecf3f3ebf5fbe48,0xbf423f5c3e60bf7f,0x3e2fbf7d3ee63f35,0x3f7ebedbbf393f62,0x3f80beacbf4a3f55,0x3ea13f4ebf51be95,0xbf58be793f7fbec4,0x3e89bf803eb83f46,
0xbf783dc93f67bf35,0x3d49bf753f183f0e,0x3f7dbef1bf2c3f6d,0x3eac3f46bf5cbe48,0xbf04bf223f710000,0x3f3ebf62be163f7b,0x3f4e3e95bf803ec4,0xbedb3f7fbe79bf55,
0x3e79bf7f3edb3f35,0x3f80be95bf4e3f55,0x3e163f62bf3ebec4,0xbf713f223f04bf7b,0x3f5cbf46beac3f80,0x3f2c3ef1bf7d3e48,0xbf183f75bd49bf6d,0xbf67bdc93f78bf0e,
0x3e893f4ebf58be48,0xbf6f3f2c3ee6bf7f,0xbd97bf673f393ec4,0x3f7cbf04bf1d3f75,0xbdfb3f78bf13bf0e,0xbf803eac3f42bf62,0x3ea1bf803ecf3f35,0x3f7abe16bf5f3f46,
0xbf773f183f09bf7b,0xbeb8bf3e3f653dc9,0x3f7fbedbbf313f6d,0x3e2f3f5cbf4abe95,0xbf7e3e793f51bf55,0x3cc9bf713f273ef1,0x3f73bd49bf6a3f35,0xbe603f7dbefcbf22,
0x3f6dbf35bec43f80,0x3ec43f35bf6d0000,0xbf6d3f353ec4bf80,0xbec4bf353f6d0000,0x3f6dbf35bec43f80,0x3ec43f35bf6d0000,0xbf6d3f353ec4bf80,0xbec4bf353f6d0000,
0x3ec43f35bf6d8000,0xbf6d3f353ec4bf80,0xbec4bf353f6d8000,0x3f6dbf35bec43f80,0x3ec43f35bf6d8000,0xbf6d3f353ec4bf80,0xbec4bf353f6d8000,0x3f6dbf35bec43f80,
0xbf4abe793f7cbf0e,0x3f31bf713d973f62,0x3f653d49bf6f3f35,0xbf093f7dbe89bf46,0xbefcbf183f7abe48,0x3f6abf3ebea13f7f,0x3f273edbbf803ec4,0xbf513f5c3dfbbf75,
0x3f1dbf783e2f3f55,0x3f393eacbf7f3ef1,0xbee63f80beb8bf35,0xbf58be163f77bf22,0x3f5fbf4ebe603f7b,0x3ecf3f2cbf733dc9,0xbf423f673cc9bf6d,0xbf13bf043f7ebe95,
0xbf043f7fbeacbf35,0xbf3ebe953f7dbf0e,0x3f4ebf62bd493f6d,0x3edb3f22bf783e48,0x3e793f46bf670000,0xbf803ef13f18bf7b,0x3e16bf753f2c3ec4,0x3f71bdc9bf5c3f55,
0xbf5cbdc93f71bf35,0x3f2cbf753e163f55,0x3f183ef1bf803ec4,0xbf673f463e79bf7b,0xbf783f223edbbf80,0xbd49bf623f4e3e48,0x3f7dbe95bf3e3f6d,0xbeac3f7fbf04bf0e,
0x3f313eacbf7e3f0e,0xbf653f4e3e2fbf75,0xbf7a3e793f42bf6d,0x3efcbf803ecf3f22,0x3f6fbf3ebe893f7b,0x3d973f5cbf58bdc9,0xbf133f7dbea1bf35,0xbf1dbedb3f80bef1,
0xbf393f71bdfbbf55,0xbee6bf183f7cbe95,0x3e60bf783f273ec4,0x3f5f3d49bf6a3f46,0x3eb83f2cbf773e48,0xbf7f3f043f09bf7f,0xbf51be163f73bf35,0x3f4abf673cc93f62,
0xbf7f3f0e3ef1bf80,0x3e95bf7b3f223ec4,0x3f463e48bf753f35,0xbf623f553dc9bf6d,0xbdc9bf553f620000,0x3f75be48bf463f6d,0xbf223f7bbe95bf35,0xbef1bf0e3f7fbec4,
0xbdc9bf553f628000,0x3f75be48bf463f6d,0xbf223f7bbe95bf35,0xbef1bf0e3f7fbec4,0x3f7fbf0ebef13f80,0xbe953f7bbf22bec4,0xbf46be483f75bf35,0x3f62bf55bdc93f6d,
0xbe2f3f71bf42be48,0xbf4abe163f6fbf46,0xbf39be793f77bf35,0x3f73bf3ebe603f75,0xbf58bd493f65bf55,0x3f5fbf5cbcc93f62,0x3f6abf4ebdfb3f6d,0xbd973f67bf51bdc9,
0xbf7c3eac3f27bf7b,0x3f1dbf7d3eb83f22,0x3f31bf783e893f35,0x3ea13f2cbf7a3e95,0x3f09bf803ee63f0e,0x3efc3f04bf803ef1,0x3ecf3f18bf7e3ec4,0xbf7f3edb3f13bf7f,
0x3f2c3e95bf783f35,0xbf7d3f223eacbf7b,0x3edbbf7f3f183ec4,0x3f043ef1bf803f0e,0x3d49bf623f5c0000,0x3f4e3dc9bf673f55,0xbf713f463e16bf6d,0x3e79bf753f3e3e48,
0xbf3e3f75be79bf35,0xbe16bf463f71be48,0x3f67bdc9bf4e3f6d,0xbf5c3f62bd49bf55,0x3f80bef1bf043f80,0xbf183f7fbedbbf0e,0xbeacbf223f7dbec4,0x3f78be95bf2c3f7b,
0x3f73be79bf313f7b,0xbf583f67bdfbbf46,0xbefc3f80bf13bec4,0xbeb8bf183f7fbef1,0xbf42be163f6abf55,0x3f7cbf2cbe893f75,0x3f4abf713e603f35,0xbcc93f5cbf653dc9,
0xbea13f78bf39be48,0xbf09bedb3f7ebf22,0xbf5f3d493f51bf6d,0x3f6fbf4ebd973f62,0x3f27bf7d3ecf3f0e,0x3e2f3f3ebf773e95,0x3f1d3eacbf7a3f35,0xbf803f043ee6bf7f,
0x3f7bbec4bf0e3f80,0xbf553f6dbe48bf35,0x3e48bf6d3f550000,0x3f0e3ec4bf7b3f35,0xbf7b3ec43f0ebf80,0x3f55bf6d3e483f35,0xbe483f6dbf550000,0xbf0ebec43f7bbf35,
0xbe483f6dbf558000,0xbf0ebec43f7bbf35,0x3f7bbec4bf0e3f80,0xbf553f6dbe48bf35,0x3e48bf6d3f558000,0x3f0e3ec4bf7b3f35,0xbf7b3ec43f0ebf80,0x3f55bf6d3e483f35,
0x3f73bf4ebcc93f55,0xbf093f80bf1dbe95,0x3efc3edbbf7c3f35,0xbf6f3e793f27bf7f,0xbf7f3f043ecfbf7b,0x3f51bf713e893f22,0xbdfbbf3e3f7abec4,0x3f393e16bf653f62,
0x3ea13f18bf803f0e,0xbf583d493f4abf75,0xbf5f3f67be2fbf35,0x3eb8bf783f423dc9,0x3d97bf5c3f6abe48,0x3f133eacbf773f46,0x3f7ebf2cbe603f6d,0xbf313f7dbee6bef1,
0x3f67bf623e163f35,0xbf043f7fbf2cbe48,0xbd49bf463f78bec4,0x3f183e95bf713f55,0xbeac3f75bf4e0000,0xbe79bf223f80bf0e,0x3f3e3dc9bf5c3f6d,0xbf7d3ef13edbbf7b,
0x3edb3ef1bf7d3f35,0xbf5c3dc93f3ebf7b,0x3f80bf22be793f6d,0xbf4e3f75beacbf0e,0xbf713e953f18bf80,0x3f78bf46bd493f55,0xbf2c3f7fbf04bec4,0x3e16bf623f67be48,
0x3f7cbf3ebd973f55,0xbf4a3f78becfbef1,0x3f313e16bf5f3f6d,0xbf733eac3f09bf7f,0xbe603f67bf653e48,0xbe89bf183f80bf22,0xbf6f3f5cbdfbbf35,0x3f27bf803f133e95,
0x3e2f3f2cbf7f3f0e,0xbf1dbe793f6abf62,0xbf393f7dbefcbec4,0x3ea1bf713f58bdc9,0xbf7a3edb3ee6bf7b,0x3f77bf4e3cc93f46,0xbeb8bf043f7ebf35,0x3f423d49bf513f75,
0xbf623e483f22bf80,0x3f7fbf0ebe953f6d,0xbf753f55bdc9bf35,0x3f46bf7b3ef13ec4,0xbef13f7bbf460000,0x3dc9bf553f75bec4,0x3e953f0ebf7f3f35,0xbf22be483f62bf6d,
0x3ef1bf7b3f468000,0xbdc93f55bf753ec4,0xbe95bf0e3f7fbf35,0x3f223e48bf623f6d,0xbf623e483f22bf80,0x3f7fbf0ebe953f6d,0xbf753f55bdc9bf35,0x3f46bf7b3ef13ec4,
0xbf39bd493f4abf7b,0x3f65be79bf133f7f,0xbe60bf183f7fbf35,0x3efc3eacbf6f3f62,0xbf6a3f67be89bf0e,0x3f42bf7d3f093e95,0xbf7c3f043ea1bf6d,0x3f7ebf3ebcc93f46,
0x3f31bf803f1d3e48,0xbee63f78bf513dc9,0x3f7abf4e3d973f35,0xbf5f3f71beb8bef1,0xbecfbedb3f77bf55,0x3f273e16bf583f75,0x3e2fbf5c3f73bec4,0x3dfb3f2cbf803f22,
0xbe16bf223f80bf35,0x3eac3ef1bf783f55,0xbf04be953f67bf6d,0x3f2c3dc9bf4e3f7b,0x3f18bf7f3f3e0000,0xbedb3f75bf5c3e48,0x3e79bf623f71bec4,0xbd493f46bf7d3f0e,
0x3f7dbf463d493f35,0xbf713f62be79bf0e,0x3f5cbf753edb3ec4,0xbf3e3f7fbf18be48,0x3f4ebdc9bf2c3f80,0xbf673e953f04bf7b,0x3f78bef1beac3f6d,0xbf803f223e16bf55,
0x3f4abf7d3f133e48,0xbf393f80bf27bdc9,0x3f65bf713ecf3ec4,0xbf583f78befcbe95,0x3f77bf5c3e603f0e,0xbf6f3f67bea1bef1,0x3f7fbf3e3cc93f35,0xbf7c3f4ebdfbbf22,
0x3f1d3e16bf513f7b,0xbf31bd493f42bf7f,0x3ee63eacbf6a3f6d,0xbf09be793f5fbf75,0x3e893f04bf7a3f55,0xbeb8bedb3f73bf62,0x3d973f2cbf803f35,0xbe2fbf183f7ebf46,
0xbf3500003f353f80,0x3f350000bf35bf80,0xbf3500003f353f80,0x3f350000bf35bf80,0xbf3500003f353f80,0x3f350000bf35bf80,0xbf3500003f353f80,0x3f350000bf35bf80,
0xbf35bf80bf358000,0x3f353f803f358000,0xbf35bf80bf358000,0x3f353f803f358000,0xbf35bf80bf358000,0x3f353f803f358000,0xbf35bf80bf358000,0x3f353f803f358000,
0xbf773f78bf7a3f7b,0xbf6f3f71bf733f75,0xbf7f3f80bf803f80,0xbf7c3f7dbf7e3f7f,0xbf4a3f4ebf513f55,0xbf393f3ebf423f46,0xbf653f67bf6a3f6d,0xbf583f5cbf5f3f62,
0x3e89be793e60be48,0x3eb8beac3ea1be95,0x3d97bd493cc98000,0x3e2fbe163dfbbdc9,0x3f1dbf183f13bf0e,0x3f31bf2c3f27bf22,0x3ee6bedb3ecfbec4,0x3f09bf043efcbef1,
0xbf183f22bf2c3f35,0xbedb3ef1bf043f0e,0xbe793e95beac3ec4,0xbd493dc9be163e48,0xbf7d3f7fbf803f80,0xbf713f75bf783f7b,0xbf5c3f62bf673f6d,0xbf3e3f46bf4e3f55,
0x3f4ebf463f3ebf35,0x3f67bf623f5cbf55,0x3f78bf753f71bf6d,0x3f80bf7f3f7dbf7b,0x3e16bdc93d498000,0x3eacbe953e79be48,0x3f04bef13edbbec4,0x3f2cbf223f18bf0e,
0x3ecfbeac3e89be48,0x3f27bf183f09bef1,0xbe2f3e79bea13ec4,0x3dfbbd49bcc93dc9,0xbf313f3ebf4a3f55,0xbee63f04bf133f22,0xbf7a3f7dbf7f3f80,0xbf5f3f67bf6f3f75,
0x3f6abf713f77bf7b,0x3f42bf4e3f58bf62,0x3f7cbf783f73bf6d,0x3f7ebf803f80bf7f,0x3f39bf2c3f1dbf0e,0x3f65bf5c3f51bf46,0x3e60be163d978000,0x3efcbedb3eb8be95,
0xbf753f7bbf7f3f80,0xbf463f55bf623f6d,0xbef13f0ebf223f35,0xbdc93e48be953ec4,0x3e95be483dc90000,0x3f22bf0e3ef1bec4,0x3f62bf553f46bf35,0x3f7fbf7b3f75bf6d,
0x3e95be483dc98000,0x3f22bf0e3ef1bec4,0x3f62bf553f46bf35,0x3f7fbf7b3f75bf6d,0x3f75bf7b3f7fbf80,0x3f46bf553f62bf6d,0x3ef1bf0e3f22bf35,0x3dc9be483e95bec4,
0xbe603eacbee63f0e,0x3e89be163cc93dc9,0xbf6f3f78bf7e3f80,0xbf273f3ebf513f62,0x3f7cbf803f7fbf7b,0x3f4abf5c3f6abf75,0x3f31bf183efcbec4,0x3f73bf673f58bf46,
0x3f7abf713f65bf55,0x3f77bf7d3f80bf7f,0x3eb8be793dfb8000,0x3f42bf2c3f13bef1,0xbe2f3d493d97be48,0xbf1d3f04becf3e95,0x3f39bf4e3f5fbf6d,0x3ea1bedb3f09bf22,
0x3f71bf623f4ebf35,0x3f78bf7f3f80bf7b,0x3f2cbf463f5cbf6d,0x3e16be953edbbf0e,0xbf673f75bf7d3f80,0xbf043f22bf3e3f55,0x3d493dc9be793ec4,0x3f18bef13eacbe48,
0x3eacbef13f18bf35,0xbe793dc93d49be48,0xbf3e3f22bf043ec4,0xbf7d3f75bf673f55,0x3edbbe953e168000,0x3f5cbf463f2cbf0e,0x3f80bf7f3f78bf6d,0x3f4ebf623f71bf7b,
0x3d97be793ecfbf0e,0xbf133edbbe893dc9,0x3f7ebf803f7abf6d,0x3f31bf4e3f65bf75,0x3ea1be16bcc93e48,0x3f58bf3e3f1dbef1,0xbf5f3f71bf7c3f80,0xbeb83f04bf273f46,
0xbf7f3f78bf6a3f55,0xbf513f67bf773f7f,0xbdfbbd493e60bec4,0xbf393f18bee63e95,0x3f73bf7d3f80bf7b,0x3f09bf2c3f4abf62,0x3efcbeac3e2f8000,0x3f6fbf5c3f42bf22,
0xbf553f6dbf7b3f80,0xbe483ec4bf0e3f35,0x3f0ebec43e480000,0x3f7bbf6d3f55bf35,0x3f55bf6d3f7bbf80,0x3e48bec43f0ebf35,0xbf0e3ec4be480000,0xbf7b3f6dbf553f35,
0x3f0ebec43e488000,0x3f7bbf6d3f55bf35,0x3f55bf6d3f7bbf80,0x3e48bec43f0ebf35,0xbf0e3ec4be488000,0xbf7b3f6dbf553f35,0xbf553f6dbf7b3f80,0xbe483ec4bf0e3f35,
0x3f42bf183ecfbe48,0x3f7cbf803f77bf62,0xbf4a3f67bf7a3f80,0xbcc93e79bee63f22,0xbf733f5cbf393f0e,0xbf583f71bf7e3f7f,0x3efcbf2c3f51bf6d,0xbeb83e163d97be95,
0x3f27bf4e3f6abf7b,0xbe2fbd493e89bef1,0x3f1dbedb3e608000,0x3f80bf783f65bf46,0xbea13f04bf313f55,0x3f09beac3dfb3dc9,0xbf5f3f3ebf133ec4,0xbf6f3f7dbf7f3f75,
0x3d49be953f04bf35,0xbf4e3f22bedb3e48,0xbf713f7fbf7d3f6d,0xbe793ef1bf2c3f55,0xbf3e3f62bf783f80,0x3e163dc9beac3f0e,0x3f67bf463f18bec4,0x3f5cbf753f80bf7b,
0xbf803f75bf5c3f35,0xbf183f46bf673f7b,0x3eacbdc9be163ec4,0x3f78bf623f3ebf0e,0x3f2cbef13e798000,0x3f7dbf7f3f71bf55,0x3edbbf223f4ebf6d,0xbf043e95bd49be48,
0xbf093f3ebf653f7b,0x3efcbe79bcc93e95,0xbecf3e163dfbbec4,0xbf7f3f71bf513f22,0x3f7cbf673f42bf0e,0x3f1dbf4e3f6fbf7f,0xbf313f5cbf773f80,0x3ea1bd49be603ef1,
0x3f58bf2c3ee6be48,0x3f5fbf783f80bf75,0xbf6a3f7dbf7e3f6d,0xbd973eacbf133f46,0x3e2fbedb3f27bf55,0xbf4a3f18beb83dc9,0x3f39bf043e898000,0x3f73bf803f7abf62,
0xbf223f55bf753f80,0x3ef1be48bdc93ec4,0x3f7fbf7b3f62bf35,0x3e95bf0e3f46bf6d,0xbf463f0ebe950000,0xbf623f7bbf7f3f6d,0x3dc93e48bef13f35,0x3f75bf553f22bec4,
0x3f46bf0e3e958000,0x3f62bf7b3f7fbf6d,0xbdc9be483ef1bf35,0xbf753f55bf223ec4,0xbf223f55bf753f80,0x3ef1be48bdc93ec4,0x3f7fbf7b3f62bf35,0x3e95bf0e3f46bf6d,
0x3f6fbf803f77bf55,0xbd97be793f09bf46,0xbf133f4ebf733f80,0x3f1dbeac3cc93e95,0x3f31bedb3dfb3e48,0x3f65bf7d3f7cbf62,0xbf7a3f5cbf273ec4,0xbefc3f3ebf6a3f7f,
0xbeb83d493e89bf0e,0xbf7f3f78bf583f22,0x3f51bf183ea18000,0x3f4abf713f80bf75,0x3f39bf673f7ebf7b,0xbee63e163e2fbef1,0xbe603f04bf423f6d,0x3f5fbf2c3ecfbdc9,
0xbf783f7fbf673f35,0x3d493e95bf183f55,0x3f7dbf623f2cbec4,0x3eacbf223f5cbf7b,0xbf043f46bf713f80,0x3f3ebef13e163e48,0x3f4ebf753f80bf6d,0xbedb3dc93e79bf0e,
0x3e793dc9bedb3f35,0x3f80bf753f4ebf0e,0x3e16bef13f3ebf6d,0xbf713f46bf043e48,0x3f5cbf223eac8000,0x3f2cbf623f7dbf7b,0xbf183e953d49bec4,0xbf673f7fbf783f55,
0x3f5fbf7d3f7abf55,0xbecf3d493ea1bf22,0xbf423f71bf803f6d,0x3f13be79bdfb3ef1,0x3f1dbf5c3f7cbf7b,0xbf393edbbd97be95,0xbee63f3ebf6f3f80,0x3f58bf183e893dc9,
0xbefc3e163e60bf0e,0xbf6a3f80bf733f46,0x3f27beacbcc93ec4,0x3f51bf783f7ebf62,0xbf4a3f04be2fbe48,0xbf313f67bf7f3f75,0x3f65bf2c3eb88000,0x3f09bf4e3f77bf7f,
0xbec43f35bf6d3f80,0x3f6dbf353ec40000,0x3ec4bf353f6dbf80,0xbf6d3f35bec40000,0xbec43f35bf6d3f80,0x3f6dbf353ec40000,0x3ec4bf353f6dbf80,0xbf6d3f35bec40000,
0x3f6dbf353ec48000,0x3ec4bf353f6dbf80,0xbf6d3f35bec48000,0xbec43f35bf6d3f80,0x3f6dbf353ec48000,0x3ec4bf353f6dbf80,0xbf6d3f35bec48000,0xbec43f35bf6d3f80,
0x3dfbbf043f51bf7b,0xbf803f67bf273e95,0xbea13f2cbf6a3f80,0x3f7abf4e3efcbdc9,0xbe89be163f09bf55,0xbf6f3f80bf653f22,0x3d973eacbf313f6d,0x3f7cbf783f4abef1,
0xbf7e3f5cbf133e48,0xbcc93edbbf423f75,0x3f73bf3e3ecf8000,0x3e60bf183f5fbf7f,0xbf773f7dbf583f0e,0x3eb83d49bee63f46,0x3f7fbf713f39bec4,0xbe2fbe793f1dbf62,
0x3f04bdc9beac3f35,0x3f3ebf753f7dbf55,0xbf4e3ef1bd49bec4,0xbedb3f46bf783f7b,0xbe793f22bf673f80,0x3f80bf623f18be48,0xbe16be953f2cbf6d,0xbf713f7fbf5c3f0e,
0x3f5cbf7f3f71bf35,0xbf2c3e953e16bf0e,0xbf183f62bf803f6d,0x3f67bf223e793e48,0x3f78bf463edb8000,0x3d49bef13f4ebf7b,0xbf7d3f75bf3e3ec4,0x3eac3dc9bf043f55,
0xbf803f67bf1d3e48,0x3ea13e16bf133f62,0x3f58bf043d973ec4,0x3e89bf2c3f6fbf7f,0xbecfbd493efcbf55,0xbf423f78bf7a3f46,0xbe2f3f18bf653f80,0x3f7ebf713f31be95,
0x3cc93edbbf4a3f7b,0x3f73bf7d3f51bef1,0x3f09bf5c3f7fbf6d,0xbf773f3ebeb8bdc9,0xbf6a3f80bf5f3f0e,0x3f27be79be603f22,0x3f7cbf4e3ee68000,0xbdfbbeac3f39bf75,
0xbdc93f0ebf623f80,0x3f75bf7b3f46bec4,0xbf223e483e95bf35,0xbef13f55bf7f3f6d,0x3f7fbf553ef10000,0xbe95be483f22bf6d,0xbf463f7bbf753f35,0x3f62bf0e3dc93ec4,
0x3f7fbf553ef18000,0xbe95be483f22bf6d,0xbf463f7bbf753f35,0x3f62bf0e3dc93ec4,0x3dc9bf0e3f62bf80,0xbf753f7bbf463ec4,0x3f22be48be953f35,0x3ef1bf553f7fbf6d,
0xbf513edb3d97bf0e,0xbdfb3f18bf6a3f7f,0xbcc93f04bf5f3f80,0x3f65bf803f58bef1,0xbe603f2cbf733f7b,0x3f77bf783f39be95,0x3f6fbf7d3f4abec4,0xbf423eac3e2fbf22,
0xbf133f67bf7f3f55,0x3f7ebf4e3ecf3dc9,0x3f80bf5c3efc8000,0xbee6bd493f09bf62,0x3f7abf3e3ea13e48,0xbe89be793f31bf75,0xbeb8be163f1dbf6d,0xbf273f71bf7c3f46,
0x3f2cbf753f78bf35,0xbf7d3f46beacbe48,0x3edb3dc9bf183f6d,0x3f04bf623f80bf55,0x3d493ef1bf5c3f80,0x3f4ebf7f3f67bf0e,0xbf713f22be16bec4,0x3e793e95bf3e3f7b,
0xbf3e3e953e79bf35,0xbe163f22bf713f7b,0x3f67bf7f3f4ebec4,0xbf5c3ef13d49bf0e,0x3f80bf623f048000,0xbf183dc93edbbf55,0xbeac3f46bf7d3f6d,0x3f78bf753f2cbe48,
0x3f65bf04bcc93f0e,0xbe60beac3f4abf7f,0x3e89bf3e3f7cbf6d,0xbf6a3f7dbf423e95,0xbf7f3f4ebeb8be48,0x3f13bd49befc3f62,0x3dfb3edbbf583f80,0x3f31bf783f73bf22,
0x3ee6bf5c3f80bf55,0xbf7a3f71bf1d3dc9,0xbf773f2cbe2fbec4,0x3ecf3e16bf273f75,0xbd973f18bf6f3f7b,0x3f51bf803f5fbef1,0x3f7ebf673f098000,0xbf393e793ea1bf46,
0x3e483ec4bf553f80,0x3f0ebf6d3f7bbf35,0xbf7b3f6dbf0e0000,0x3f55bec4be483f35,0xbe48bec43f55bf80,0xbf0e3f6dbf7b3f35,0x3f7bbf6d3f0e0000,0xbf553ec43e48bf35,
0x3f7bbf6d3f0e8000,0xbf553ec43e48bf35,0x3e483ec4bf553f80,0x3f0ebf6d3f7bbf35,0xbf7b3f6dbf0e8000,0x3f55bec4be483f35,0xbe48bec43f55bf80,0xbf0e3f6dbf7b3f35,
0xbf653f7dbf393e48,0x3f7abf2c3dfb3ef1,0x3e893eacbf513f80,0x3ecfbf5c3f7fbf46,0x3f27bf783f6fbf0e,0xbf7c3f67befcbdc9,0xbf1d3d493f09bf6d,0xbcc93f18bf733f75,
0x3ee63e16bf313f7b,0x3e60bf3e3f7ebf62,0x3f77bf713f138000,0xbf6a3f043d97bf22,0xbf423e793eb8bf55,0x3e2f3edbbf5f3f7f,0xbf4a3f80bf583ec4,0x3f80bf4e3ea13e95,
0xbf673ef13e16bf35,0x3f043dc9bf2c3f7b,0x3d49bf223f78bf6d,0xbf183f75bf713f0e,0x3eac3e95bf4e3f80,0x3e79bf463f80bf55,0xbf3e3f7fbf5c3ec4,0x3f7dbf623edb3e48,
0xbedb3f62bf7d3f35,0x3f5cbf7f3f3ebe48,0xbf803f46be79bec4,0x3f4ebe95beac3f55,0x3f71bf753f188000,0xbf783f22bd49bf0e,0x3f2cbdc9bf043f6d,0xbe16bef13f67bf7b,
0xbf13bd493f27bf7b,0x3dfb3f04bf6f3f75,0xbf803f4ebe89bec4,0x3f65bedbbe603f46,0xbf093f71bf733f0e,0x3f5fbf7d3f31bdc9,0x3ecf3e79bf4a3f80,0x3d97bf2c3f7cbf62,
0xbf513f80bf423e48,0x3f7ebf5c3eb83e95,0x3cc93f18bf773f6d,0x3ee6bf673f7abf22,0x3f58beacbea13f55,0xbefcbe163f39bf7f,0x3f6abf783f1d8000,0xbf7f3f3ebe2fbef1,
0x3ef13e48bf463f80,0xbdc9bf0e3f75bf6d,0xbe953f55bf7f3f35,0x3f22bf7b3f62bec4,0xbf623f7bbf220000,0x3f7fbf553e953ec4,0xbf753f0e3dc9bf35,0x3f46be48bef13f6d,
0x3f62bf7b3f228000,0xbf7f3f55be95bec4,0x3f75bf0ebdc93f35,0xbf463e483ef1bf6d,0x3ef13e48bf463f80,0xbdc9bf0e3f75bf6d,0xbe953f55bf7f3f35,0x3f22bf7b3f62bec4,
0xbcc93f2cbf7e3f55,0x3ea1bf5c3f7cbf22,0x3f093e16bf423f80,0xbe89bedb3f6abf75,0xbf6f3f71befcbe48,0x3f7fbf4e3e603ef1,0xbf133f78bf653ec4,0x3f4abf803f39bdc9,
0x3f80bf3e3dfb3f0e,0xbf733f043e2fbf46,0x3f58bf7d3f278000,0xbf773f67becfbe95,0x3eb83eacbf5f3f7b,0xbd97bf183f7abf62,0x3f51be79bee63f6d,0xbf1dbd493f31bf7f,
0xbe163f46bf803f35,0x3eacbf623f78bf0e,0xbf043f75bf673ec4,0x3f2cbf7f3f4ebe48,0x3f183dc9bf3e3f80,0xbedbbe953f5cbf7b,0x3e793ef1bf713f6d,0xbd49bf223f7dbf55,
0x3f7dbf22bd493f35,0xbf713ef13e79bf55,0x3f5cbe95bedb3f6d,0xbf3e3dc93f18bf7b,0x3f4ebf7f3f2c8000,0xbf673f75bf04be48,0x3f78bf623eac3ec4,0xbf803f46be16bf0e,
0x3dfb3f18bf7c3f55,0xbcc9bf2c3f7fbf46,0x3ea13edbbf6f3f6d,0xbe60bf043f77bf62,0x3efc3e79bf583f7b,0xbecfbeac3f65bf75,0x3f273d49bf393f80,0xbf13be163f4abf7f,
0x3f7ebf4e3e2f3f0e,0xbf803f3ebd97bf22,0x3f73bf673eb83ec4,0xbf7a3f5cbe89bef1,0x3f5fbf783f093e48,0xbf6a3f71bee6be95,0x3f42bf803f318000,0xbf513f7dbf1dbdc9,
0xbf3500003f353f80,0x3f350000bf35bf80,0xbf3500003f353f80,0x3f350000bf35bf80,0xbf3500003f353f80,0x3f350000bf35bf80,0xbf3500003f353f80,0x3f350000bf35bf80,
0xbf35bf80bf358000,0x3f353f803f358000,0xbf35bf80bf358000,0x3f353f803f358000,0xbf35bf80bf358000,0x3f353f803f358000,0xbf35bf80bf358000,0x3f353f803f358000,
0xbefc3f04bf093f0e,0xbecf3edbbee63ef1,0xbf273f2cbf313f35,0xbf133f18bf1d3f22,0xbdfb3e16be2f3e48,0xbcc93d49bd973dc9,0xbea13eacbeb83ec4,0xbe603e79be893e95,
0x3f5fbf5c3f58bf55,0x3f6abf673f65bf62,0x3f42bf3e3f39bf35,0x3f51bf4e3f4abf46,0x3f7ebf7d3f7cbf7b,0x3f80bf803f7fbf7f,0x3f73bf713f6fbf6d,0x3f7abf783f77bf75,
0x3f4ebf463f3ebf35,0x3f67bf623f5cbf55,0x3f78bf753f71bf6d,0x3f80bf7f3f7dbf7b,0x3e16bdc93d490000,0x3eacbe953e79be48,0x3f04bef13edbbec4,0x3f2cbf223f18bf0e,
0x3f18bf223f2cbf35,0x3edbbef13f04bf0e,0x3e79be953eacbec4,0x3d49bdc93e16be48,0x3f7dbf7f3f80bf80,0x3f71bf753f78bf7b,0x3f5cbf623f67bf6d,0x3f3ebf463f4ebf55,
0x3eb8bedb3efcbf0e,0x3d97be163e60be95,0x3f51bf5c3f65bf6d,0x3f1dbf2c3f39bf46,0x3f80bf803f7ebf7b,0x3f73bf783f7cbf7f,0x3f58bf4e3f42bf35,0x3f77bf713f6abf62,
0xbf6f3f67bf5f3f55,0xbf7f3f7dbf7a3f75,0xbf133f04bee63ec4,0xbf4a3f3ebf313f22,0xbcc9bd493dfbbe48,0xbea13e79be2f3dc9,0x3f09bf183f27bf35,0x3e89beac3ecfbef1,
0x3f75bf7b3f7fbf80,0x3f46bf553f62bf6d,0x3ef1bf0e3f22bf35,0x3dc9be483e95bec4,0xbe953e48bdc90000,0xbf223f0ebef13ec4,0xbf623f55bf463f35,0xbf7f3f7bbf753f6d,
0xbe953e48bdc98000,0xbf223f0ebef13ec4,0xbf623f55bf463f35,0xbf7f3f7bbf753f6d,0xbf753f7bbf7f3f80,0xbf463f55bf623f6d,0xbef13f0ebf223f35,0xbdc93e48be953ec4,
0xbf093edbbea13e48,0xbf5f3f4ebf393f22,0x3ecfbf043f1dbf35,0xbd97bd493e2fbe95,0xbf133f2cbf423f55,0xbdfb3e79beb83ef1,0xbf803f7dbf773f6d,0xbf653f71bf7a3f7f,
0xbf583f67bf733f7b,0xbefc3f18bf313f46,0xbf6a3f5cbf4a3f35,0xbf7f3f80bf7c3f75,0x3f51bf3e3f27bf0e,0x3f7ebf783f6fbf62,0xbcc93e16be893ec4,0x3ee6beac3e60bdc9,
0xbeac3ef1bf183f35,0x3e79bdc9bd493e48,0x3f3ebf223f04bec4,0x3f7dbf753f67bf55,0xbedb3e95be160000,0xbf5c3f46bf2c3f0e,0xbf803f7fbf783f6d,0xbf4e3f62bf713f7b,
0x3f71bf623f4ebf35,0x3f78bf7f3f80bf7b,0x3f2cbf463f5cbf6d,0x3e16be953edbbf0e,0xbf673f75bf7d3f80,0xbf043f22bf3e3f55,0x3d493dc9be793ec4,0x3f18bef13eacbe48,
0x3f42bf5c3f6fbf7b,0x3e2fbeac3efcbf22,0x3f4abf2c3f09bec4,0x3f80bf7d3f73bf62,0xbee63f18bf393f55,0x3e60bd49bdfb3e95,0xbf773f67bf513f35,0xbf6a3f78bf7f3f7f,
0xbf273f04beb83e48,0xbf7c3f71bf5f3f46,0x3f1dbf3e3f58bf6d,0xbcc9be163ea1bef1,0x3f65bf4e3f31bf0e,0x3f7abf803f7ebf75,0xbe893edbbf133f35,0x3ecfbe793d973dc9,
0xbf553f6dbf7b3f80,0xbe483ec4bf0e3f35,0x3f0ebec43e480000,0x3f7bbf6d3f55bf35,0x3f55bf6d3f7bbf80,0x3e48bec43f0ebf35,0xbf0e3ec4be480000,0xbf7b3f6dbf553f35,
0x3f0ebec43e488000,0x3f7bbf6d3f55bf35,0x3f55bf6d3f7bbf80,0x3e48bec43f0ebf35,0xbf0e3ec4be488000,0xbf7b3f6dbf553f35,0xbf553f6dbf7b3f80,0xbe483ec4bf0e3f35,
0x3f7fbf7d3f6fbf55,0x3f13bf3e3f5fbf75,0xbdfb3eacbf093f35,0x3f31bf043ea1bdc9,0xbf653f78bf803f7b,0xbe603edbbf1d3f46,0xbe893d493e2fbec4,0xbf6a3f4ebf273ef1,
0xbd97be163eb8bf0e,0xbf513f2cbefc3e95,0x3f7ebf713f58bf35,0x3f39bf5c3f73bf7f,0x3ee6be793cc93e48,0x3f7abf673f4abf22,0xbf773f80bf7c3f6d,0xbecf3f18bf423f62,
0xbf803f75bf5c3f35,0xbf183f46bf673f7b,0x3eacbdc9be163ec4,0x3f78bf623f3ebf0e,0x3f2cbef13e790000,0x3f7dbf7f3f71bf55,0x3edbbf223f4ebf6d,0xbf043e95bd49be48,
0xbd493e95bf043f35,0x3f4ebf223edbbe48,0x3f71bf7f3f7dbf6d,0x3e79bef13f2cbf55,0x3f3ebf623f78bf80,0xbe16bdc93eacbf0e,0xbf673f46bf183ec4,0xbf5c3f75bf803f7b,
0x3f7abf803f73bf55,0x3e89bf043f39bf62,0xbeb83f18bf4a3f6d,0x3f27bedb3e2f3dc9,0xbf133eacbd97be48,0xbf7e3f7dbf6a3f46,0x3f80bf783f5fbf35,0x3ee6bf2c3f58bf75,
0xbe60bd493ea1bf0e,0xbf773f5cbf313ef1,0x3f6fbf4e3f1dbec4,0x3f42bf673f7cbf7f,0xbf513f71bf7f3f7b,0x3dfb3e16becf3f22,0xbcc9be793efcbf35,0xbf653f3ebf093e95,
0x3f22bf553f75bf80,0xbef13e483dc9bec4,0xbf7f3f7bbf623f35,0xbe953f0ebf463f6d,0x3f46bf0e3e950000,0x3f62bf7b3f7fbf6d,0xbdc9be483ef1bf35,0xbf753f55bf223ec4,
0xbf463f0ebe958000,0xbf623f7bbf7f3f6d,0x3dc93e48bef13f35,0x3f75bf553f22bec4,0x3f22bf553f75bf80,0xbef13e483dc9bec4,0xbf7f3f7bbf623f35,0xbe953f0ebf463f6d,
0xbecf3f2cbf5f3f7b,0x3f42bf043e603dc9,0xbe2fbe163ee6bf35,0xbf7e3f67bf393ef1,0xbf803f71bf4a3f0e,0xbea13f18bf513f75,0x3f58bf783f7fbf6d,0xbe89bd493eb8bf22,
0x3f6abf3e3efcbe48,0x3f27bf5c3f7abf7f,0xbf7c3f7dbf653f35,0xbdfb3edbbf313f62,0xbcc93eacbf1d3f55,0x3f73bf4e3f13be95,0xbf093e793d97bec4,0xbf773f80bf6f3f46,
0xbe79bdc93edbbf35,0xbf803f75bf4e3f0e,0xbe163ef1bf3e3f6d,0x3f71bf463f04be48,0xbf5c3f22beac0000,0xbf2c3f62bf7d3f7b,0x3f18be95bd493ec4,0x3f67bf7f3f78bf55,
0xbf783f7fbf673f35,0x3d493e95bf183f55,0x3f7dbf623f2cbec4,0x3eacbf223f5cbf7b,0xbf043f46bf713f80,0x3f3ebef13e163e48,0x3f4ebf753f80bf6d,0xbedb3dc93e79bf0e,
0x3f77bf4e3f09be48,0x3eb8bf2c3f65bf7f,0xbf7f3f67bf313ec4,0xbe2f3f04bf4a3f75,0x3f7ebf783f51bf0e,0xbcc9beac3f27bf62,0xbf733f80bf6a3f35,0x3e603e16befc3f46,
0x3e89bf183f58bf7b,0xbf6f3f3ebee63dc9,0xbd973edbbf393f6d,0x3f7cbf5c3f1dbe95,0xbdfbbe793f13bf55,0xbf803f71bf423ef1,0x3ea13d49becf3f35,0x3f7abf7d3f5fbf22,
0xbec43f35bf6d3f80,0x3f6dbf353ec40000,0x3ec4bf353f6dbf80,0xbf6d3f35bec40000,0xbec43f35bf6d3f80,0x3f6dbf353ec40000,0x3ec4bf353f6dbf80,0xbf6d3f35bec40000,
0x3f6dbf353ec48000,0x3ec4bf353f6dbf80,0xbf6d3f35bec48000,0xbec43f35bf6d3f80,0x3f6dbf353ec48000,0x3ec4bf353f6dbf80,0xbf6d3f35bec48000,0xbec43f35bf6d3f80,
0xbf1d3e793e2fbf0e,0xbf393f71bf7f3f62,0x3ee6bd49beb83f35,0x3f58bf7d3f77bf46,0xbf5f3f18be60be48,0xbecf3f3ebf733f7f,0x3f42bedb3cc93ec4,0x3f13bf5c3f7ebf75,
0xbf4a3f78bf7c3f55,0x3f31beacbd973ef1,0x3f65bf803f6fbf35,0xbf093e163e89bf22,0xbefc3f4ebf7a3f7b,0x3f6abf2c3ea13dc9,0x3f27bf673f80bf6d,0xbf513f04bdfbbe95,
0x3f5cbf7f3f71bf35,0xbf2c3e953e16bf0e,0xbf183f62bf803f6d,0x3f67bf223e793e48,0x3f78bf463edb0000,0x3d49bef13f4ebf7b,0xbf7d3f75bf3e3ec4,0x3eac3dc9bf043f55,
0xbf043dc93eacbf35,0xbf3e3f75bf7d3f55,0x3f4ebef13d493ec4,0x3edbbf463f78bf7b,0x3e79bf223f67bf80,0xbf803f62bf183e48,0x3e163e95bf2c3f6d,0x3f71bf7f3f5cbf0e,
0x3f39beacbdfb3f0e,0x3ee6bf4e3f7cbf75,0xbe60be793f27bf6d,0xbf5f3f80bf6a3f22,0xbeb83f3ebf773f7b,0x3f7fbf5c3f09bdc9,0x3f51bf7d3f73bf35,0xbf4a3edb3cc9bef1,
0x3f31bf713f7ebf55,0xbf653f18be2fbe95,0xbf7a3f78bf423ec4,0x3efcbd49becf3f46,0x3f6fbf2c3e893e48,0x3d97bf043f58bf7f,0xbf133e163ea1bf35,0xbf1d3f67bf803f62,
0x3dc9bf0e3f62bf80,0xbf753f7bbf463ec4,0x3f22be48be953f35,0x3ef1bf553f7fbf6d,0xbf7f3f55bef10000,0x3e953e48bf223f6d,0x3f46bf7b3f75bf35,0xbf623f0ebdc9bec4,
0xbf7f3f55bef18000,0x3e953e48bf223f6d,0x3f46bf7b3f75bf35,0xbf623f0ebdc9bec4,0xbdc93f0ebf623f80,0x3f75bf7b3f46bec4,0xbf223e483e95bf35,0xbef13f55bf7f3f6d,
0x3f7cbf713f27be48,0xbf1d3e163eb8bf46,0xbf313e793e89bf35,0xbea13f3ebf7a3f75,0xbf093d493ee6bf55,0xbefc3f5cbf803f62,0xbecf3f4ebf7e3f6d,0x3f7fbf673f13bdc9,
0xbe2fbeac3f42bf7b,0xbf4a3f7dbf6f3f22,0xbf393f78bf773f35,0x3f73bf2c3e603e95,0xbf583f80bf653f0e,0x3f5fbf043cc93ef1,0x3f6abf183dfb3ec4,0xbd97bedb3f51bf7f,
0x3f3ebe95be793f35,0x3e16bf223f71bf7b,0xbf673f7fbf4e3ec4,0x3f5cbef1bd493f0e,0xbf803f62bf040000,0x3f18bdc9bedb3f55,0x3eacbf463f7dbf6d,0xbf783f75bf2c3e48,
0x3f2cbf753f78bf35,0xbf7d3f46beacbe48,0x3edb3dc9bf183f6d,0x3f04bf623f80bf55,0x3d493ef1bf5c3f80,0x3f4ebf7f3f67bf0e,0xbf713f22be16bec4,0x3e793e95bf3e3f7b,
0x3ea13e79bf393f7b,0x3f09bf673f7ebf46,0x3f5fbf803f51bec4,0xbf6f3f18bd97bef1,0xbf273e163ecfbf55,0xbe2f3f2cbf773f75,0xbf1d3f71bf7a3f35,0x3f80bf5c3ee63dc9,
0x3f73bf783f31be48,0xbf583edb3dfbbf22,0xbefcbd493f13bf6d,0xbeb83f4ebf7f3f62,0xbf423f7dbf6a3f0e,0x3f7cbf3e3e893e95,0x3f4abeacbe603f35,0xbcc9bf043f65bf7f,
0x3e483ec4bf553f80,0x3f0ebf6d3f7bbf35,0xbf7b3f6dbf0e0000,0x3f55bec4be483f35,0xbe48bec43f55bf80,0xbf0e3f6dbf7b3f35,0x3f7bbf6d3f0e0000,0xbf553ec43e48bf35,
0x3f7bbf6d3f0e8000,0xbf553ec43e48bf35,0x3e483ec4bf553f80,0x3f0ebf6d3f7bbf35,0xbf7b3f6dbf0e8000,0x3f55bec4be483f35,0xbe48bec43f55bf80,0xbf0e3f6dbf7b3f35,
0xbea13f4ebf803f55,0x3f58bf803f4abe95,0x3f5fbedbbe2f3f35,0xbeb8be793f42bf7f,0xbd97bf043f6abf7b,0xbf133f71bf773f22,0xbf7e3f3ebe60bec4,0x3f31be16bee63f62,
0x3f73bf183cc93f0e,0xbf09bd493f1dbf75,0x3efcbf673f7cbf35,0xbf6f3f78bf273dc9,0xbf7f3f5cbecfbe48,0x3f51beacbe893f46,0xbdfb3f2cbf7a3f6d,0x3f39bf7d3f65bef1,
0xbedb3f62bf7d3f35,0x3f5cbf7f3f3ebe48,0xbf803f46be79bec4,0x3f4ebe95beac3f55,0x3f71bf753f180000,0xbf783f22bd49bf0e,0x3f2cbdc9bf043f6d,0xbe16bef13f67bf7b,
0x3f67bef1be163f35,0xbf04bdc93f2cbf7b,0xbd493f22bf783f6d,0x3f18bf753f71bf0e,0xbeacbe953f4ebf80,0xbe793f46bf803f55,0x3f3ebf7f3f5cbec4,0xbf7d3f62bedbbe48,
0xbe2f3f3ebf7f3f55,0x3f1dbf783f6abef1,0x3f39be16befc3f6d,0xbea1beac3f58bf7f,0x3f7abf673ee63e48,0xbf773f183cc9bf22,0x3eb8bf5c3f7ebf35,0xbf423f80bf513e95,
0x3f7cbf2c3d973f0e,0xbf4a3e793ecfbf62,0x3f31bf7d3f5fbec4,0xbf733f71bf09bdc9,0xbe60bedb3f65bf7b,0xbe893f4ebf803f46,0xbf6f3f043dfbbf35,0x3f27bd49bf133f75,
0xbef1be483f46bf80,0x3dc93f0ebf753f6d,0x3e95bf553f7fbf35,0xbf223f7bbf623ec4,0x3f62bf7b3f220000,0xbf7f3f55be95bec4,0x3f75bf0ebdc93f35,0xbf463e483ef1bf6d,
0xbf623f7bbf228000,0x3f7fbf553e953ec4,0xbf753f0e3dc9bf35,0x3f46be48bef13f6d,0xbef1be483f46bf80,0x3dc93f0ebf753f6d,0x3e95bf553f7fbf35,0xbf223f7bbf623ec4,
0xbf313d493f1dbf7b,0x3ee63e79bf513f7f,0xbf7a3f183d97bf35,0x3f5fbeacbeb83f62,0x3ecfbf673f77bf0e,0xbf273f7dbf583e95,0xbe2fbf043f73bf6d,0xbdfb3f3ebf803f46,
0xbf393f80bf4a3e48,0x3f65bf783f133dc9,0xbe603f4ebf7f3f35,0x3efcbf713f6fbef1,0xbf6a3edb3e89bf55,0x3f42be16bf093f75,0xbf7c3f5cbea1bec4,0x3f7ebf2c3cc93f22,
0xbf7d3f223d49bf35,0x3f71bef1be793f55,0xbf5c3e953edbbf6d,0x3f3ebdc9bf183f7b,0xbf4e3f7fbf2c0000,0x3f67bf753f043e48,0xbf783f62beacbec4,0x3f80bf463e163f0e,
0xbe163f46bf803f35,0x3eacbf623f78bf0e,0xbf043f75bf673ec4,0x3f2cbf7f3f4ebe48,0x3f183dc9bf3e3f80,0xbedbbe953f5cbf7b,0x3e793ef1bf713f6d,0xbd49bf223f7dbf55,
0xbf1d3f7dbf513e48,0x3f31bf803f42bdc9,0xbee63f71bf6a3ec4,0x3f09bf783f5fbe95,0xbe893f5cbf7a3f0e,0x3eb8bf673f73bef1,0xbd973f3ebf803f35,0x3e2fbf4e3f7ebf22,
0x3f4abe16bf133f7b,0xbf393d493f27bf7f,0x3f65beacbecf3f6d,0xbf583e793efcbf75,0x3f77bf04be603f55,0xbf6f3edb3ea1bf62,0x3f7fbf2cbcc93f35,0xbf7c3f183dfbbf46,
0x3f350000bf353f80,0xbf3500003f35bf80,0x3f350000bf353f80,0xbf3500003f35bf80,0x3f350000bf353f80,0xbf3500003f35bf80,0x3f350000bf353f80,0xbf3500003f35bf80,
0xbf353f80bf358000,0x3f35bf803f358000,0xbf353f80bf358000,0x3f35bf803f358000,0xbf353f80bf358000,0x3f35bf803f358000,0xbf353f80bf358000,0x3f35bf803f358000,
0xbe89bf783e603f7b,0xbeb8bf713ea13f75,0xbd97bf803cc93f80,0xbe2fbf7d3dfb3f7f,0xbf1dbf4e3f133f55,0xbf31bf3e3f273f46,0xbee6bf673ecf3f6d,0xbf09bf5c3efc3f62,
0xbf773e793f7abe48,0xbf6f3eac3f73be95,0xbf7f3d493f808000,0xbf7c3e163f7ebdc9,0xbf4a3f183f51bf0e,0xbf393f2c3f42bf22,0xbf653edb3f6abec4,0xbf583f043f5fbef1,
0xbf4ebf223f3e3f35,0xbf67bef13f5c3f0e,0xbf78be953f713ec4,0xbf80bdc93f7d3e48,0xbe16bf7f3d493f80,0xbeacbf753e793f7b,0xbf04bf623edb3f6d,0xbf2cbf463f183f55,
0xbf183f463f2cbf35,0xbedb3f623f04bf55,0xbe793f753eacbf6d,0xbd493f7f3e16bf7b,0xbf7d3dc93f808000,0xbf713e953f78be48,0xbf5c3ef13f67bec4,0xbf3e3f223f4ebf0e,
0xbf6a3eac3f77be48,0xbf423f183f58bef1,0xbf7cbe793f733ec4,0xbf7e3d493f803dc9,0xbf39bf3e3f1d3f55,0xbf65bf043f513f22,0xbe60bf7d3d973f80,0xbefcbf673eb83f75,
0x3ecf3f71be89bf7b,0x3f273f4ebf09bf62,0xbe2f3f783ea1bf6d,0x3dfb3f803cc9bf7f,0xbf313f2c3f4abf0e,0xbee63f5c3f13bf46,0xbf7a3e163f7f8000,0xbf5f3edb3f6fbe95,
0xbe95bf7b3dc93f80,0xbf22bf553ef13f6d,0xbf62bf0e3f463f35,0xbf7fbe483f753ec4,0xbf753e483f7f0000,0xbf463f0e3f62bec4,0xbef13f553f22bf35,0xbdc93f7b3e95bf6d,
0xbf753e483f7f8000,0xbf463f0e3f62bec4,0xbef13f553f22bf35,0xbdc93f7b3e95bf6d,0x3e953f7bbdc9bf80,0x3f223f55bef1bf6d,0x3f623f0ebf46bf35,0x3f7f3e48bf75bec4,
0xbf7abeac3f653f0e,0xbf773e163f803dc9,0xbeb8bf783dfb3f80,0xbf42bf3e3f133f62,0x3e2f3f803d97bf7b,0x3f1d3f5cbecfbf75,0xbf393f183f5fbec4,0xbea13f673f09bf46,
0xbe603f713ee6bf55,0x3e893f7dbcc9bf7f,0xbf6f3e793f7e8000,0xbf273f2c3f51bef1,0x3f7cbd49bf7fbe48,0x3f4abf04bf6a3e95,0x3f313f4ebefcbf6d,0x3f733edbbf58bf22,
0xbeac3f623f18bf35,0x3e793f7f3d49bf7b,0x3f3e3f46bf04bf6d,0x3f7d3e95bf67bf0e,0xbedbbf753e163f80,0xbf5cbf223f2c3f55,0xbf80bdc93f783ec4,0xbf4e3ef13f71be48,
0x3f713ef1bf4ebf35,0x3f78bdc9bf80be48,0x3f2cbf22bf5c3ec4,0x3e16bf75bedb3f55,0xbf673e953f7d8000,0xbf043f463f3ebf0e,0x3d493f7f3e79bf6d,0x3f183f62beacbf7b,
0x3f7f3e79bf6abf0e,0x3f51bedbbf773dc9,0x3dfb3f803e60bf6d,0x3f393f4ebee6bf75,0xbf733e163f803e48,0xbf093f3e3f4abef1,0xbefcbf713e2f3f80,0xbf6fbf043f423f46,
0x3d97bf78becf3f55,0xbf13bf673e893f7f,0x3f7e3d49bf7abec4,0x3f31bf18bf653e95,0x3ea13f7d3cc9bf7b,0x3f583f2cbf1dbf62,0xbf5f3eac3f7c8000,0xbeb83f5c3f27bf22,
0xbf0ebf6d3e483f80,0xbf7bbec43f553f35,0xbf553ec43f7b0000,0xbe483f6d3f0ebf35,0x3f0e3f6dbe48bf80,0x3f7b3ec4bf55bf35,0x3f55bec4bf7b0000,0x3e48bf6dbf0e3f35,
0xbf553ec43f7b8000,0xbe483f6d3f0ebf35,0x3f0e3f6dbe48bf80,0x3f7b3ec4bf55bf35,0x3f55bec4bf7b8000,0x3e48bf6dbf0e3f35,0xbf0ebf6d3e483f80,0xbf7bbec43f553f35,
0xbf273f183f6abe48,0x3e2f3f803e89bf62,0xbf1dbf673e603f80,0xbf80be793f653f22,0x3ea1bf5cbf313f0e,0xbf09bf713dfb3f7f,0x3f5f3f2cbf13bf6d,0x3f6fbe16bf7fbe95,
0x3f423f4ebecfbf7b,0x3f7c3d49bf77bef1,0xbf4a3edb3f7a8000,0xbcc93f783ee6bf46,0xbf73bf043f393f55,0xbf583eac3f7e3dc9,0x3efcbf3ebf513ec4,0xbeb8bf7dbd973f75,
0x3f803e95bf5cbf35,0x3f18bf22bf673e48,0xbeacbf7fbe163f6d,0xbf78bef13f3e3f55,0xbf2cbf623e793f80,0xbf7dbdc93f713f0e,0xbedb3f463f4ebec4,0x3f043f75bd49bf7b,
0x3d49bf75bf043f35,0xbf4ebf463edb3f7b,0xbf713dc93f7d3ec4,0xbe793f623f2cbf0e,0xbf3e3ef13f788000,0x3e163f7f3eacbf55,0x3f673f22bf18bf6d,0x3f5cbe95bf80be48,
0xbf58bf3e3ee63f7b,0xbf5f3e793f803e95,0x3f6abe16bf7ebec4,0x3d97bf71bf133f22,0xbe2f3f673f27bf0e,0x3f4a3f4ebeb8bf7f,0xbf39bf5c3e893f80,0xbf733d493f7a3ef1,
0xbf093f2c3f65be48,0x3efc3f783cc9bf75,0xbecfbf7dbdfb3f6d,0xbf7fbeac3f513f46,0x3f7c3edbbf42bf55,0x3f1dbf18bf6f3dc9,0xbf313f043f778000,0x3ea13f803e60bf62,
0xbf46bf553e953f80,0xbf623e483f7f3ec4,0x3dc93f7b3ef1bf35,0x3f753f0ebf22bf6d,0x3f22bf0ebf750000,0xbef1bf7bbdc93f6d,0xbf7fbe483f623f35,0xbe953f553f46bec4,
0xbf223f0e3f758000,0x3ef13f7b3dc9bf6d,0x3f7f3e48bf62bf35,0x3e95bf55bf463ec4,0xbf46bf553e953f80,0xbf623e483f7f3ec4,0x3dc93f7b3ef1bf35,0x3f753f0ebf22bf6d,
0x3eb83f803e89bf55,0x3f7f3e79bf58bf46,0xbf51bf4e3ea13f80,0xbf4a3eac3f803e95,0xbf393edb3f7e3e48,0x3ee63f7d3e2fbf62,0x3e60bf5cbf423ec4,0xbf5fbf3e3ecf3f7f,
0x3f6fbd49bf77bf0e,0xbd97bf78bf093f22,0xbf133f183f738000,0x3f1d3f71bcc9bf75,0x3f313f67bdfbbf7b,0x3f65be16bf7cbef1,0xbf7abf043f273f6d,0xbefc3f2c3f6abdc9,
0xbe79bf7fbedb3f35,0xbf80be953f4e3f55,0xbe163f623f3ebec4,0x3f713f22bf04bf7b,0xbf5cbf463eac3f80,0xbf2c3ef13f7d3e48,0x3f183f753d49bf6d,0x3f67bdc9bf78bf0e,
0xbf78bdc93f673f35,0x3d493f753f18bf0e,0x3f7d3ef1bf2cbf6d,0x3eacbf46bf5c3e48,0xbf043f223f718000,0x3f3e3f62be16bf7b,0x3f4ebe95bf80bec4,0xbedbbf7fbe793f55,
0x3efc3f7d3e60bf55,0x3f6abd49bf73bf22,0xbf27bf71bcc93f6d,0xbf513e793f7e3ef1,0x3f4a3f5cbe2fbf7b,0x3f31bedbbf7fbe95,0xbf65bf3e3eb83f80,0xbf093f183f773dc9,
0x3f5fbe16bf7abf0e,0xbecfbf80bea13f46,0xbf423eac3f803ec4,0x3f133f783dfbbf62,0x3f1dbf04bf7cbe48,0xbf39bf673d973f75,0xbee63f2c3f6f8000,0x3f583f4ebe89bf7f,
0xbf6dbf353ec43f80,0xbec43f353f6d0000,0x3f6d3f35bec4bf80,0x3ec4bf35bf6d0000,0xbf6dbf353ec43f80,0xbec43f353f6d0000,0x3f6d3f35bec4bf80,0x3ec4bf35bf6d0000,
0xbec43f353f6d8000,0x3f6d3f35bec4bf80,0x3ec4bf35bf6d8000,0xbf6dbf353ec43f80,0xbec43f353f6d8000,0x3f6d3f35bec4bf80,0x3ec4bf35bf6d8000,0xbf6dbf353ec43f80,
0x3f7e3f04bf13bf7b,0x3cc9bf67bf423e95,0xbf73bf2c3ecf3f80,0xbe603f4e3f5fbdc9,0x3f773e16bf58bf55,0xbeb8bf80bee63f22,0xbf7fbeac3f393f6d,0x3e2f3f783f1dbef1,
0x3dfbbf5cbf513e48,0xbf80bedb3f273f75,0xbea13f3e3f6a8000,0x3f7a3f18befcbf7f,0xbe89bf7dbf093f0e,0xbf6fbd493f653f46,0x3d973f713f31bec4,0x3f7c3e79bf4abf62,
0xbf5c3dc93f713f35,0x3f2c3f753e16bf55,0x3f18bef1bf80bec4,0xbf67bf463e793f7b,0xbf78bf223edb3f80,0xbd493f623f4ebe48,0x3f7d3e95bf3ebf6d,0xbeacbf7fbf043f0e,
0x3f043f7f3eacbf35,0x3f3ebe95bf7dbf0e,0xbf4ebf623d493f6d,0xbedb3f223f783e48,0xbe793f463f678000,0x3f803ef1bf18bf7b,0xbe16bf75bf2c3ec4,0xbf71bdc93f5c3f55,
0xbcc9bf67bf4a3e48,0xbf73be163f513f62,0xbf093f043f7f3ec4,0x3f773f2cbeb8bf7f,0x3f6a3d49bf5fbf55,0xbf27bf78be603f46,0xbf7cbf183ee63f80,0x3dfb3f713f39be95,
0xbf80bedb3f1d3f7b,0x3ea13f7d3f13bef1,0x3f583f5cbd97bf6d,0x3e89bf3ebf6fbdc9,0xbecfbf80befc3f0e,0xbf423e793f7a3f22,0xbe2f3f4e3f658000,0x3f7e3eacbf31bf75,
0xbf7fbf0e3ef13f80,0x3e953f7b3f22bec4,0x3f46be48bf75bf35,0xbf62bf553dc93f6d,0xbdc93f553f620000,0x3f753e48bf46bf6d,0xbf22bf7bbe953f35,0xbef13f0e3f7f3ec4,
0xbdc93f553f628000,0x3f753e48bf46bf6d,0xbf22bf7bbe953f35,0xbef13f0e3f7f3ec4,0x3f7f3f0ebef1bf80,0xbe95bf7bbf223ec4,0xbf463e483f753f35,0x3f623f55bdc9bf6d,
0x3f13bedbbf7fbf0e,0xbf7ebf183ecf3f7f,0xbf80bf043efc3f80,0x3ee63f803f09bef1,0xbf7abf2c3ea13f7b,0x3e893f783f31be95,0x3eb83f7d3f1dbec4,0x3f27beacbf7cbf22,
0xbf51bf67bd973f55,0xbdfb3f4e3f6a3dc9,0xbcc93f5c3f5f8000,0x3f653d49bf58bf62,0xbe603f3e3f733e48,0x3f773e79bf39bf75,0x3f6f3e16bf4abf6d,0xbf42bf71be2f3f46,
0x3f3e3f753e79bf35,0x3e16bf46bf71be48,0xbf67bdc93f4e3f6d,0x3f5c3f623d49bf55,0xbf80bef13f043f80,0x3f183f7f3edbbf0e,0x3eacbf22bf7dbec4,0xbf78be953f2c3f7b,
0x3f2cbe95bf78bf35,0xbf7dbf223eac3f7b,0x3edb3f7f3f18bec4,0x3f04bef1bf80bf0e,0x3d493f623f5c8000,0x3f4ebdc9bf67bf55,0xbf71bf463e163f6d,0x3e793f753f3ebe48,
0xbee63f043f803f0e,0x3f7a3eacbf1dbf7f,0x3f773f3ebe2fbf6d,0xbecfbf7dbf273e95,0x3d97bf4ebf6fbe48,0xbf513d493f5f3f62,0xbf7ebedb3f093f80,0x3f393f783ea1bf22,
0x3f653f5c3cc9bf55,0xbe60bf71bf4a3dc9,0x3e89bf2cbf7cbec4,0xbf6abe163f423f75,0xbf7fbf183eb83f7b,0x3f133f803efcbef1,0x3dfb3f673f588000,0x3f31be79bf73bf46,
0xbf7bbec43f0e3f80,0x3f553f6d3e48bf35,0xbe48bf6dbf550000,0xbf0e3ec43f7b3f35,0x3f7b3ec4bf0ebf80,0xbf55bf6dbe483f35,0x3e483f6d3f550000,0x3f0ebec4bf7bbf35,
0x3e483f6d3f558000,0x3f0ebec4bf7bbf35,0xbf7bbec43f0e3f80,0x3f553f6d3e48bf35,0xbe48bf6dbf558000,0xbf0e3ec43f7b3f35,0x3f7b3ec4bf0ebf80,0xbf55bf6dbe483f35,
0xbee6bf7dbf313e48,0xbe603f2c3f7e3ef1,0xbf77beac3f133f80,0x3f6a3f5c3d97bf46,0x3f423f783eb8bf0e,0xbe2fbf67bf5fbdc9,0x3f4abd49bf58bf6d,0xbf80bf183ea13f75,
0xbf65be163f393f7b,0x3f7a3f3ebdfbbf62,0x3e893f713f518000,0x3ecfbf04bf7fbf22,0x3f27be79bf6fbf55,0xbf7cbedb3efc3f7f,0xbf1dbf80bf093ec4,0xbcc93f4e3f733e95,
0x3edbbef1bf7dbf35,0xbf5cbdc93f3e3f7b,0x3f803f22be79bf6d,0xbf4ebf75beac3f0e,0xbf71be953f183f80,0x3f783f46bd49bf55,0xbf2cbf7fbf043ec4,0x3e163f623f673e48,
0xbf67bf62be163f35,0x3f043f7f3f2cbe48,0x3d49bf46bf78bec4,0xbf183e953f713f55,0x3eac3f753f4e8000,0x3e79bf22bf80bf0e,0xbf3e3dc93f5c3f6d,0x3f7d3ef1bedbbf7b,
0x3f513d49bf42bf7b,0xbf7ebf043eb83f75,0xbcc9bf4ebf77bec4,0xbee63edb3f7a3f46,0xbf58bf71bea13f0e,0x3efc3f7d3f39bdc9,0xbf6abe793f1d3f80,0x3f7f3f2cbe2fbf62,
0xbf13bf80bf273e48,0x3dfb3f5c3f6f3e95,0xbf80bf183e893f6d,0x3f653f673e60bf22,0xbf093eac3f733f55,0x3f5f3e16bf31bf7f,0x3ecf3f783f4a8000,0x3d97bf3ebf7cbef1,
0xbf62be483f223f80,0x3f7f3f0ebe95bf6d,0xbf75bf55bdc93f35,0x3f463f7b3ef1bec4,0xbef1bf7bbf460000,0x3dc93f553f753ec4,0x3e95bf0ebf7fbf35,0xbf223e483f623f6d,
0x3ef13f7b3f468000,0xbdc9bf55bf75bec4,0xbe953f0e3f7f3f35,0x3f22be48bf62bf6d,0xbf62be483f223f80,0x3f7f3f0ebe95bf6d,0xbf75bf55bdc93f35,0x3f463f7b3ef1bec4,
0xbf80bf2c3dfb3f55,0x3f733f5c3e2fbf22,0xbf58be163f273f80,0x3f773edbbecfbf75,0xbeb8bf71bf5fbe48,0x3d973f4e3f7a3ef1,0xbf51bf78bee63ec4,0x3f1d3f803f31bdc9,
0xbcc93f3e3f7e3f0e,0x3ea1bf04bf7cbf46,0x3f093f7d3f428000,0xbe89bf67bf6abe95,0xbf6fbeac3efc3f7b,0x3f7f3f18be60bf62,0xbf133e793f653f6d,0x3f4a3d49bf39bf7f,
0xbf7dbf46bd493f35,0x3f713f623e79bf0e,0xbf5cbf75bedb3ec4,0x3f3e3f7f3f18be48,0xbf4ebdc93f2c3f80,0x3f673e95bf04bf7b,0xbf78bef13eac3f6d,0x3f803f22be16bf55,
0xbe163f223f803f35,0x3eacbef1bf78bf55,0xbf043e953f673f6d,0x3f2cbdc9bf4ebf7b,0x3f183f7f3f3e8000,0xbedbbf75bf5cbe48,0x3e793f623f713ec4,0xbd49bf46bf7dbf0e,
0xbf7ebf183e2f3f55,0x3f803f2cbd97bf46,0xbf73bedb3eb83f6d,0x3f7a3f04be89bf62,0xbf5fbe793f093f7b,0x3f6a3eacbee6bf75,0xbf42bd493f313f80,0x3f513e16bf1dbf7f,
0x3dfb3f4e3f7c3f0e,0xbcc9bf3ebf7fbf22,0x3ea13f673f6f3ec4,0xbe60bf5cbf77bef1,0x3efc3f783f583e48,0xbecfbf71bf65be95,0x3f273f803f398000,0xbf13bf7dbf4abdc9,
0x3f350000bf353f80,0xbf3500003f35bf80,0x3f350000bf353f80,0xbf3500003f35bf80,0x3f350000bf353f80,0xbf3500003f35bf80,0x3f350000bf353f80,0xbf3500003f35bf80,
0xbf353f80bf358000,0x3f35bf803f358000,0xbf353f80bf358000,0x3f35bf803f358000,0xbf353f80bf358000,0x3f35bf803f358000,0xbf353f80bf358000,0x3f35bf803f358000,
0xbf5fbf043f583f0e,0xbf6abedb3f653ef1,0xbf42bf2c3f393f35,0xbf51bf183f4a3f22,0xbf7ebe163f7c3e48,0xbf80bd493f7f3dc9,0xbf73beac3f6f3ec4,0xbf7abe793f773e95,
0xbefc3f5c3f09bf55,0xbecf3f673ee6bf62,0xbf273f3e3f31bf35,0xbf133f4e3f1dbf46,0xbdfb3f7d3e2fbf7b,0xbcc93f803d97bf7f,0xbea13f713eb8bf6d,0xbe603f783e89bf75,
0xbf183f463f2cbf35,0xbedb3f623f04bf55,0xbe793f753eacbf6d,0xbd493f7f3e16bf7b,0xbf7d3dc93f800000,0xbf713e953f78be48,0xbf5c3ef13f67bec4,0xbf3e3f223f4ebf0e,
0x3f4e3f22bf3ebf35,0x3f673ef1bf5cbf0e,0x3f783e95bf71bec4,0x3f803dc9bf7dbe48,0x3e163f7fbd49bf80,0x3eac3f75be79bf7b,0x3f043f62bedbbf6d,0x3f2c3f46bf18bf55,
0x3f6f3edbbf5fbf0e,0x3f7f3e16bf7abe95,0x3f133f5cbee6bf6d,0x3f4a3f2cbf31bf46,0x3cc93f803dfbbf7b,0x3ea13f78be2fbf7f,0xbf093f4e3f27bf35,0xbe893f713ecfbf62,
0x3eb8bf67befc3f55,0x3d97bf7dbe603f75,0x3f51bf04bf653ec4,0x3f1dbf3ebf393f22,0x3f803d49bf7ebe48,0x3f73be79bf7c3dc9,0x3f583f18bf42bf35,0x3f773eacbf6abef1,
0x3e953f7bbdc9bf80,0x3f223f55bef1bf6d,0x3f623f0ebf46bf35,0x3f7f3e48bf75bec4,0x3f75be48bf7f0000,0x3f46bf0ebf623ec4,0x3ef1bf55bf223f35,0x3dc9bf7bbe953f6d,
0x3f75be48bf7f8000,0x3f46bf0ebf623ec4,0x3ef1bf55bf223f35,0x3dc9bf7bbe953f6d,0xbe95bf7b3dc93f80,0xbf22bf553ef13f6d,0xbf62bf0e3f463f35,0xbf7fbe483f753ec4,
0x3f58bedbbf733e48,0x3efcbf4ebf313f22,0x3f6a3f04bf4abf35,0x3f7f3d49bf7cbe95,0xbf51bf2c3f273f55,0xbf7ebe793f6f3ef1,0x3cc9bf7dbe893f6d,0xbee6bf713e603f7f,
0xbf09bf673ea13f7b,0xbf5fbf183f393f46,0x3ecfbf5cbf1d3f35,0xbd97bf80be2f3f75,0xbf133f3e3f42bf0e,0xbdfb3f783eb8bf62,0xbf80be163f773ec4,0xbf653eac3f7abdc9,
0xbf71bef13f4e3f35,0xbf783dc93f803e48,0xbf2c3f223f5cbec4,0xbe163f753edbbf55,0x3f67be95bf7d0000,0x3f04bf46bf3e3f0e,0xbd49bf7fbe793f6d,0xbf18bf623eac3f7b,
0xbeac3f623f18bf35,0x3e793f7f3d49bf7b,0x3f3e3f46bf04bf6d,0x3f7d3e95bf67bf0e,0xbedbbf753e163f80,0xbf5cbf223f2c3f55,0xbf80bdc93f783ec4,0xbf4e3ef13f71be48,
0x3f273f5cbeb8bf7b,0x3f7c3eacbf5fbf22,0xbf1d3f2c3f58bec4,0x3cc93f7d3ea1bf62,0xbf65bf183f313f55,0xbf7a3d493f7e3e95,0x3e89bf67bf133f35,0xbecfbf783d973f7f,
0x3f42bf04bf6f3e48,0x3e2fbf71befc3f46,0x3f4a3f3ebf09bf6d,0x3f803e16bf73bef1,0xbee63f4e3f39bf0e,0x3e603f803dfbbf75,0xbf77bedb3f513f35,0xbf6a3e793f7f3dc9,
0xbf0ebf6d3e483f80,0xbf7bbec43f553f35,0xbf553ec43f7b0000,0xbe483f6d3f0ebf35,0x3f0e3f6dbe48bf80,0x3f7b3ec4bf55bf35,0x3f55bec4bf7b0000,0x3e48bf6dbf0e3f35,
0xbf553ec43f7b8000,0xbe483f6d3f0ebf35,0x3f0e3f6dbe48bf80,0x3f7b3ec4bf55bf35,0x3f55bec4bf7b8000,0x3e48bf6dbf0e3f35,0xbf0ebf6d3e483f80,0xbf7bbec43f553f35,
0x3d973f7d3eb8bf55,0x3f513f3ebefcbf75,0xbf7ebeac3f583f35,0xbf393f043f73bdc9,0xbee6bf783cc93f7b,0xbf7abedb3f4a3f46,0x3f77bd49bf7cbec4,0x3ecfbf4ebf423ef1,
0x3f7f3e16bf6fbf0e,0x3f13bf2cbf5f3e95,0xbdfb3f713f09bf35,0x3f313f5cbea1bf7f,0xbf653e793f803e48,0xbe603f673f1dbf22,0xbe89bf80be2f3f6d,0xbf6abf183f273f62,
0x3d49bf75bf043f35,0xbf4ebf463edb3f7b,0xbf713dc93f7d3ec4,0xbe793f623f2cbf0e,0xbf3e3ef13f780000,0x3e163f7f3eacbf55,0x3f673f22bf18bf6d,0x3f5cbe95bf80be48,
0xbf80be953f5c3f35,0xbf183f223f67be48,0x3eac3f7f3e16bf6d,0x3f783ef1bf3ebf55,0x3f2c3f62be79bf80,0x3f7d3dc9bf71bf0e,0x3edbbf46bf4e3ec4,0xbf04bf753d493f7b,
0x3e603f803ea1bf55,0x3f773f04bf31bf62,0xbf6fbf183f1d3f6d,0xbf423edb3f7c3dc9,0x3f51beacbf7fbe48,0xbdfbbf7dbecf3f46,0x3cc93f783efcbf35,0x3f653f2cbf09bf75,
0x3f7a3d49bf73bf0e,0x3e89bf5cbf393ef1,0xbeb83f4e3f4abec4,0x3f273f67be2fbf7f,0xbf13bf713d973f7b,0xbf7ebe163f6a3f22,0x3f803e79bf5fbf35,0x3ee6bf3ebf583e95,
0x3f463f55be95bf80,0x3f62be48bf7fbec4,0xbdc9bf7bbef13f35,0xbf75bf0e3f223f6d,0xbf223f0e3f750000,0x3ef13f7b3dc9bf6d,0x3f7f3e48bf62bf35,0x3e95bf55bf463ec4,
0x3f22bf0ebf758000,0xbef1bf7bbdc93f6d,0xbf7fbe483f623f35,0xbe953f553f46bec4,0x3f463f55be95bf80,0x3f62be48bf7fbec4,0xbdc9bf7bbef13f35,0xbf75bf0e3f223f6d,
0xbf6abf2c3efc3f7b,0xbf273f043f7a3dc9,0x3f7c3e16bf65bf35,0x3dfbbf67bf313ef1,0x3cc9bf71bf1d3f0e,0xbf73bf183f133f75,0x3f093f783d97bf6d,0x3f773d49bf6fbf22,
0xbecf3f3e3f5fbe48,0x3f423f5cbe60bf7f,0xbe2fbf7dbee63f35,0xbf7ebedb3f393f62,0xbf80beac3f4a3f55,0xbea13f4e3f51be95,0x3f58be79bf7fbec4,0xbe89bf80beb83f46,
0x3f783dc9bf67bf35,0xbd49bf75bf183f0e,0xbf7dbef13f2c3f6d,0xbeac3f463f5cbe48,0x3f04bf22bf710000,0xbf3ebf623e163f7b,0xbf4e3e953f803ec4,0x3edb3f7f3e79bf55,
0xbe79bf7fbedb3f35,0xbf80be953f4e3f55,0xbe163f623f3ebec4,0x3f713f22bf04bf7b,0xbf5cbf463eac3f80,0xbf2c3ef13f7d3e48,0x3f183f753d49bf6d,0x3f67bdc9bf78bf0e,
0xbe893f4e3f58be48,0x3f6f3f2cbee6bf7f,0x3d97bf67bf393ec4,0xbf7cbf043f1d3f75,0x3dfb3f783f13bf0e,0x3f803eacbf42bf62,0xbea1bf80becf3f35,0xbf7abe163f5f3f46,
0x3f773f18bf09bf7b,0x3eb8bf3ebf653dc9,0xbf7fbedb3f313f6d,0xbe2f3f5c3f4abe95,0x3f7e3e79bf51bf55,0xbcc9bf71bf273ef1,0xbf73bd493f6a3f35,0x3e603f7d3efcbf22,
0xbf6dbf353ec43f80,0xbec43f353f6d0000,0x3f6d3f35bec4bf80,0x3ec4bf35bf6d0000,0xbf6dbf353ec43f80,0xbec43f353f6d0000,0x3f6d3f35bec4bf80,0x3ec4bf35bf6d0000,
0xbec43f353f6d8000,0x3f6d3f35bec4bf80,0x3ec4bf35bf6d8000,0xbf6dbf353ec43f80,0xbec43f353f6d8000,0x3f6d3f35bec4bf80,0x3ec4bf35bf6d8000,0xbf6dbf353ec43f80,
0x3f4abe79bf7cbf0e,0xbf31bf71bd973f62,0xbf653d493f6f3f35,0x3f093f7d3e89bf46,0x3efcbf18bf7abe48,0xbf6abf3e3ea13f7f,0xbf273edb3f803ec4,0x3f513f5cbdfbbf75,
0xbf1dbf78be2f3f55,0xbf393eac3f7f3ef1,0x3ee63f803eb8bf35,0x3f58be16bf77bf22,0xbf5fbf4e3e603f7b,0xbecf3f2c3f733dc9,0x3f423f67bcc9bf6d,0x3f13bf04bf7ebe95,
0x3f043f7f3eacbf35,0x3f3ebe95bf7dbf0e,0xbf4ebf623d493f6d,0xbedb3f223f783e48,0xbe793f463f670000,0x3f803ef1bf18bf7b,0xbe16bf75bf2c3ec4,0xbf71bdc93f5c3f55,
0x3f5cbdc9bf71bf35,0xbf2cbf75be163f55,0xbf183ef13f803ec4,0x3f673f46be79bf7b,0x3f783f22bedbbf80,0x3d49bf62bf4e3e48,0xbf7dbe953f3e3f6d,0x3eac3f7f3f04bf0e,
0xbf313eac3f7e3f0e,0x3f653f4ebe2fbf75,0x3f7a3e79bf42bf6d,0xbefcbf80becf3f22,0xbf6fbf3e3e893f7b,0xbd973f5c3f58bdc9,0x3f133f7d3ea1bf35,0x3f1dbedbbf80bef1,
0x3f393f713dfbbf55,0x3ee6bf18bf7cbe95,0xbe60bf78bf273ec4,0xbf5f3d493f6a3f46,0xbeb83f2c3f773e48,0x3f7f3f04bf09bf7f,0x3f51be16bf73bf35,0xbf4abf67bcc93f62,
0x3f7f3f0ebef1bf80,0xbe95bf7bbf223ec4,0xbf463e483f753f35,0x3f623f55bdc9bf6d,0x3dc9bf55bf620000,0xbf75be483f463f6d,0x3f223f7b3e95bf35,0x3ef1bf0ebf7fbec4,
0x3dc9bf55bf628000,0xbf75be483f463f6d,0x3f223f7b3e95bf35,0x3ef1bf0ebf7fbec4,0xbf7fbf0e3ef13f80,0x3e953f7b3f22bec4,0x3f46be48bf75bf35,0xbf62bf553dc93f6d,
0x3e2f3f713f42be48,0x3f4abe16bf6fbf46,0x3f39be79bf77bf35,0xbf73bf3e3e603f75,0x3f58bd49bf65bf55,0xbf5fbf5c3cc93f62,0xbf6abf4e3dfb3f6d,0x3d973f673f51bdc9,
0x3f7c3eacbf27bf7b,0xbf1dbf7dbeb83f22,0xbf31bf78be893f35,0xbea13f2c3f7a3e95,0xbf09bf80bee63f0e,0xbefc3f043f803ef1,0xbecf3f183f7e3ec4,0x3f7f3edbbf13bf7f,
0xbf2c3e953f783f35,0x3f7d3f22beacbf7b,0xbedbbf7fbf183ec4,0xbf043ef13f803f0e,0xbd49bf62bf5c0000,0xbf4e3dc93f673f55,0x3f713f46be16bf6d,0xbe79bf75bf3e3e48,
0x3f3e3f753e79bf35,0x3e16bf46bf71be48,0xbf67bdc93f4e3f6d,0x3f5c3f623d49bf55,0xbf80bef13f043f80,0x3f183f7f3edbbf0e,0x3eacbf22bf7dbec4,0xbf78be953f2c3f7b,
0xbf73be793f313f7b,0x3f583f673dfbbf46,0x3efc3f803f13bec4,0x3eb8bf18bf7fbef1,0x3f42be16bf6abf55,0xbf7cbf2c3e893f75,0xbf4abf71be603f35,0x3cc93f5c3f653dc9,
0x3ea13f783f39be48,0x3f09bedbbf7ebf22,0x3f5f3d49bf51bf6d,0xbf6fbf4e3d973f62,0xbf27bf7dbecf3f0e,0xbe2f3f3e3f773e95,0xbf1d3eac3f7a3f35,0x3f803f04bee6bf7f,
0xbf7bbec43f0e3f80,0x3f553f6d3e48bf35,0xbe48bf6dbf550000,0xbf0e3ec43f7b3f35,0x3f7b3ec4bf0ebf80,0xbf55bf6dbe483f35,0x3e483f6d3f550000,0x3f0ebec4bf7bbf35,
0x3e483f6d3f558000,0x3f0ebec4bf7bbf35,0xbf7bbec43f0e3f80,0x3f553f6d3e48bf35,0xbe48bf6dbf558000,0xbf0e3ec43f7b3f35,0x3f7b3ec4bf0ebf80,0xbf55bf6dbe483f35,
0xbf73bf4e3cc93f55,0x3f093f803f1dbe95,0xbefc3edb3f7c3f35,0x3f6f3e79bf27bf7f,0x3f7f3f04becfbf7b,0xbf51bf71be893f22,0x3dfbbf3ebf7abec4,0xbf393e163f653f62,
0xbea13f183f803f0e,0x3f583d49bf4abf75,0x3f5f3f673e2fbf35,0xbeb8bf78bf423dc9,0xbd97bf5cbf6abe48,0xbf133eac3f773f46,0xbf7ebf2c3e603f6d,0x3f313f7d3ee6bef1,
0xbf67bf62be163f35,0x3f043f7f3f2cbe48,0x3d49bf46bf78bec4,0xbf183e953f713f55,0x3eac3f753f4e0000,0x3e79bf22bf80bf0e,0xbf3e3dc93f5c3f6d,0x3f7d3ef1bedbbf7b,
0xbedb3ef13f7d3f35,0x3f5c3dc9bf3ebf7b,0xbf80bf223e793f6d,0x3f4e3f753eacbf0e,0x3f713e95bf18bf80,0xbf78bf463d493f55,0x3f2c3f7f3f04bec4,0xbe16bf62bf67be48,
0xbf7cbf3e3d973f55,0x3f4a3f783ecfbef1,0xbf313e163f5f3f6d,0x3f733eacbf09bf7f,0x3e603f673f653e48,0x3e89bf18bf80bf22,0x3f6f3f5c3dfbbf35,0xbf27bf80bf133e95,
0xbe2f3f2c3f7f3f0e,0x3f1dbe79bf6abf62,0x3f393f7d3efcbec4,0xbea1bf71bf58bdc9,0x3f7a3edbbee6bf7b,0xbf77bf4ebcc93f46,0x3eb8bf04bf7ebf35,0xbf423d493f513f75,
0x3f623e48bf22bf80,0xbf7fbf0e3e953f6d,0x3f753f553dc9bf35,0xbf46bf7bbef13ec4,0x3ef13f7b3f460000,0xbdc9bf55bf75bec4,0xbe953f0e3f7f3f35,0x3f22be48bf62bf6d,
0xbef1bf7bbf468000,0x3dc93f553f753ec4,0x3e95bf0ebf7fbf35,0xbf223e483f623f6d,0x3f623e48bf22bf80,0xbf7fbf0e3e953f6d,0x3f753f553dc9bf35,0xbf46bf7bbef13ec4,
0x3f39bd49bf4abf7b,0xbf65be793f133f7f,0x3e60bf18bf7fbf35,0xbefc3eac3f6f3f62,0x3f6a3f673e89bf0e,0xbf42bf7dbf093e95,0x3f7c3f04bea1bf6d,0xbf7ebf3e3cc93f46,
0xbf31bf80bf1d3e48,0x3ee63f783f513dc9,0xbf7abf4ebd973f35,0x3f5f3f713eb8bef1,0x3ecfbedbbf77bf55,0xbf273e163f583f75,0xbe2fbf5cbf73bec4,0xbdfb3f2c3f803f22,
0x3e16bf22bf80bf35,0xbeac3ef13f783f55,0x3f04be95bf67bf6d,0xbf2c3dc93f4e3f7b,0xbf18bf7fbf3e0000,0x3edb3f753f5c3e48,0xbe79bf62bf71bec4,0x3d493f463f7d3f0e,
0xbf7dbf46bd493f35,0x3f713f623e79bf0e,0xbf5cbf75bedb3ec4,0x3f3e3f7f3f18be48,0xbf4ebdc93f2c3f80,0x3f673e95bf04bf7b,0xbf78bef13eac3f6d,0x3f803f22be16bf55,
0xbf4abf7dbf133e48,0x3f393f803f27bdc9,0xbf65bf71becf3ec4,0x3f583f783efcbe95,0xbf77bf5cbe603f0e,0x3f6f3f673ea1bef1,0xbf7fbf3ebcc93f35,0x3f7c3f4e3dfbbf22,
0xbf1d3e163f513f7b,0x3f31bd49bf42bf7f,0xbee63eac3f6a3f6d,0x3f09be79bf5fbf75,0xbe893f043f7a3f55,0x3eb8bedbbf73bf62,0xbd973f2c3f803f35,0x3e2fbf18bf7ebf46,
0x3f003f003f003f00,0x3f003f003f003f00,0x3f003f003f003f00,0x3f003f003f003f00,0x3f003f003f003f00,0x3f003f003f003f00,0x3f003f003f003f00,0x3f003f003f003f00,
0xbf003f00bf003f00,0xbf003f00bf003f00,0xbf003f00bf003f00,0xbf003f00bf003f00,0xbf003f00bf003f00,0xbf003f00bf003f00,0xbf003f00bf003f00,0xbf003f00bf003f00,
0xbe89be79be60be48,0xbeb8beacbea1be95,0xbd97bd49bcc90000,0xbe2fbe16bdfbbdc9,0xbf1dbf18bf13bf0e,0xbf31bf2cbf27bf22,0xbee6bedbbecfbec4,0xbf09bf04befcbef1,
0xbf77bf78bf7abf7b,0xbf6fbf71bf73bf75,0xbf7fbf80bf80bf80,0xbf7cbf7dbf7ebf7f,0xbf4abf4ebf51bf55,0xbf39bf3ebf42bf46,0xbf65bf67bf6abf6d,0xbf58bf5cbf5fbf62,
0xbf18bf22bf2cbf35,0xbedbbef1bf04bf0e,0xbe79be95beacbec4,0xbd49bdc9be16be48,0xbf7dbf7fbf80bf80,0xbf71bf75bf78bf7b,0xbf5cbf62bf67bf6d,0xbf3ebf46bf4ebf55,
0x3f4e3f463f3e3f35,0x3f673f623f5c3f55,0x3f783f753f713f6d,0x3f803f7f3f7d3f7b,0x3e163dc93d498000,0x3eac3e953e793e48,0x3f043ef13edb3ec4,0x3f2c3f223f183f0e,
0x3f6a3f713f773f7b,0x3f423f4e3f583f62,0x3f7c3f783f733f6d,0x3f7e3f803f803f7f,0x3f393f2c3f1d3f0e,0x3f653f5c3f513f46,0x3e603e163d970000,0x3efc3edb3eb83e95,
0xbecfbeacbe89be48,0xbf27bf18bf09bef1,0x3e2f3e793ea13ec4,0xbdfbbd493cc93dc9,0x3f313f3e3f4a3f55,0x3ee63f043f133f22,0x3f7a3f7d3f7f3f80,0x3f5f3f673f6f3f75,
0x3f753f7b3f7f3f80,0x3f463f553f623f6d,0x3ef13f0e3f223f35,0x3dc93e483e953ec4,0xbe95be48bdc90000,0xbf22bf0ebef1bec4,0xbf62bf55bf46bf35,0xbf7fbf7bbf75bf6d,
0xbe95be48bdc98000,0xbf22bf0ebef1bec4,0xbf62bf55bf46bf35,0xbf7fbf7bbf75bf6d,0xbf75bf7bbf7fbf80,0xbf46bf55bf62bf6d,0xbef1bf0ebf22bf35,0xbdc9be48be95bec4,
0xbf7abf71bf65bf55,0xbf77bf7dbf80bf7f,0xbeb8be79bdfb0000,0xbf42bf2cbf13bef1,0x3e2f3d49bd97be48,0x3f1d3f043ecf3e95,0xbf39bf4ebf5fbf6d,0xbea1bedbbf09bf22,
0xbe60beacbee6bf0e,0x3e893e163cc9bdc9,0xbf6fbf78bf7ebf80,0xbf27bf3ebf51bf62,0x3f7c3f803f7f3f7b,0x3f4a3f5c3f6a3f75,0x3f313f183efc3ec4,0x3f733f673f583f46,
0x3f713f623f4e3f35,0x3f783f7f3f803f7b,0x3f2c3f463f5c3f6d,0x3e163e953edb3f0e,0xbf67bf75bf7dbf80,0xbf04bf22bf3ebf55,0x3d49bdc9be79bec4,0x3f183ef13eac3e48,
0x3eac3ef13f183f35,0xbe79bdc93d493e48,0xbf3ebf22bf04bec4,0xbf7dbf75bf67bf55,0x3edb3e953e168000,0x3f5c3f463f2c3f0e,0x3f803f7f3f783f6d,0x3f4e3f623f713f7b,
0xbf7fbf78bf6abf55,0xbf51bf67bf77bf7f,0xbdfb3d493e603ec4,0xbf39bf18bee6be95,0x3f733f7d3f803f7b,0x3f093f2c3f4a3f62,0x3efc3eac3e2f0000,0x3f6f3f5c3f423f22,
0xbd97be79becfbf0e,0x3f133edb3e893dc9,0xbf7ebf80bf7abf6d,0xbf31bf4ebf65bf75,0xbea1be163cc93e48,0xbf58bf3ebf1dbef1,0x3f5f3f713f7c3f80,0x3eb83f043f273f46,
0x3f553f6d3f7b3f80,0x3e483ec43f0e3f35,0xbf0ebec4be480000,0xbf7bbf6dbf55bf35,0xbf55bf6dbf7bbf80,0xbe48bec4bf0ebf35,0x3f0e3ec43e480000,0x3f7b3f6d3f553f35,
0xbf0ebec4be488000,0xbf7bbf6dbf55bf35,0xbf55bf6dbf7bbf80,0xbe48bec4bf0ebf35,0x3f0e3ec43e488000,0x3f7b3f6d3f553f35,0x3f553f6d3f7b3f80,0x3e483ec43f0e3f35,
0xbf27bf4ebf6abf7b,0x3e2fbd49be89bef1,0xbf1dbedbbe600000,0xbf80bf78bf65bf46,0x3ea13f043f313f55,0xbf09beacbdfb3dc9,0x3f5f3f3e3f133ec4,0x3f6f3f7d3f7f3f75,
0x3f423f183ecf3e48,0x3f7c3f803f773f62,0xbf4abf67bf7abf80,0xbcc9be79bee6bf22,0xbf73bf5cbf39bf0e,0xbf58bf71bf7ebf7f,0x3efc3f2c3f513f6d,0xbeb8be163d973e95,
0x3d493e953f043f35,0xbf4ebf22bedbbe48,0xbf71bf7fbf7dbf6d,0xbe79bef1bf2cbf55,0xbf3ebf62bf78bf80,0x3e16bdc9beacbf0e,0x3f673f463f183ec4,0x3f5c3f753f803f7b,
0xbf80bf75bf5cbf35,0xbf18bf46bf67bf7b,0x3eac3dc9be16bec4,0x3f783f623f3e3f0e,0x3f2c3ef13e798000,0x3f7d3f7f3f713f55,0x3edb3f223f4e3f6d,0xbf04be95bd493e48,
0x3f583f2c3ee63e48,0x3f5f3f783f803f75,0xbf6abf7dbf7ebf6d,0xbd97beacbf13bf46,0x3e2f3edb3f273f55,0xbf4abf18beb8bdc9,0x3f393f043e890000,0x3f733f803f7a3f62,
0x3f093f3e3f653f7b,0xbefcbe793cc93e95,0x3ecf3e16bdfbbec4,0x3f7f3f713f513f22,0xbf7cbf67bf42bf0e,0xbf1dbf4ebf6fbf7f,0x3f313f5c3f773f80,0xbea1bd493e603ef1,
0x3f223f553f753f80,0xbef1be483dc93ec4,0xbf7fbf7bbf62bf35,0xbe95bf0ebf46bf6d,0x3f463f0e3e950000,0x3f623f7b3f7f3f6d,0xbdc93e483ef13f35,0xbf75bf55bf22bec4,
0xbf46bf0ebe958000,0xbf62bf7bbf7fbf6d,0x3dc9be48bef1bf35,0x3f753f553f223ec4,0x3f223f553f753f80,0xbef1be483dc93ec4,0xbf7fbf7bbf62bf35,0xbe95bf0ebf46bf6d,
0x3eb83d49be89bf0e,0x3f7f3f783f583f22,0xbf51bf18bea10000,0xbf4abf71bf80bf75,0xbf39bf67bf7ebf7b,0x3ee63e16be2fbef1,0x3e603f043f423f6d,0xbf5fbf2cbecfbdc9,
0x3f6f3f803f773f55,0xbd973e793f093f46,0xbf13bf4ebf73bf80,0x3f1d3eac3cc9be95,0x3f313edb3dfbbe48,0x3f653f7d3f7c3f62,0xbf7abf5cbf27bec4,0xbefcbf3ebf6abf7f,
0xbf78bf7fbf67bf35,0x3d49be95bf18bf55,0x3f7d3f623f2c3ec4,0x3eac3f223f5c3f7b,0xbf04bf46bf71bf80,0x3f3e3ef13e16be48,0x3f4e3f753f803f6d,0xbedbbdc93e793f0e,
0x3e79bdc9bedbbf35,0x3f803f753f4e3f0e,0x3e163ef13f3e3f6d,0xbf71bf46bf04be48,0x3f5c3f223eac8000,0x3f2c3f623f7d3f7b,0xbf18be953d493ec4,0xbf67bf7fbf78bf55,
0xbefcbe163e603f0e,0xbf6abf80bf73bf46,0x3f273eacbcc9bec4,0x3f513f783f7e3f62,0xbf4abf04be2f3e48,0xbf31bf67bf7fbf75,0x3f653f2c3eb80000,0x3f093f4e3f773f7f,
0xbf5fbf7dbf7abf55,0x3ecf3d49bea1bf22,0x3f423f713f803f6d,0xbf13be793dfb3ef1,0xbf1dbf5cbf7cbf7b,0x3f393edb3d97be95,0x3ee63f3e3f6f3f80,0xbf58bf18be893dc9,
0x3ec43f353f6d3f80,0xbf6dbf35bec40000,0xbec4bf35bf6dbf80,0x3f6d3f353ec40000,0x3ec43f353f6d3f80,0xbf6dbf35bec40000,0xbec4bf35bf6dbf80,0x3f6d3f353ec40000,
0xbf6dbf35bec48000,0xbec4bf35bf6dbf80,0x3f6d3f353ec48000,0x3ec43f353f6d3f80,0xbf6dbf35bec48000,0xbec4bf35bf6dbf80,0x3f6d3f353ec48000,0x3ec43f353f6d3f80,
0x3f7e3f5c3f133e48,0x3cc93edb3f423f75,0xbf73bf3ebecf0000,0xbe60bf18bf5fbf7f,0x3f773f7d3f583f0e,0xbeb83d493ee63f46,0xbf7fbf71bf39bec4,0x3e2fbe79bf1dbf62,
0x3dfb3f043f513f7b,0xbf80bf67bf27be95,0xbea1bf2cbf6abf80,0x3f7a3f4e3efc3dc9,0xbe893e163f093f55,0xbf6fbf80bf65bf22,0x3d97beacbf31bf6d,0x3f7c3f783f4a3ef1,
0x3f043dc9beacbf35,0x3f3e3f753f7d3f55,0xbf4ebef1bd493ec4,0xbedbbf46bf78bf7b,0xbe79bf22bf67bf80,0x3f803f623f183e48,0xbe163e953f2c3f6d,0xbf71bf7fbf5cbf0e,
0x3f5c3f7f3f713f35,0xbf2cbe953e163f0e,0xbf18bf62bf80bf6d,0x3f673f223e79be48,0x3f783f463edb8000,0x3d493ef13f4e3f7b,0xbf7dbf75bf3ebec4,0x3eacbdc9bf04bf55,
0x3cc9bedbbf4abf7b,0x3f733f7d3f513ef1,0x3f093f5c3f7f3f6d,0xbf77bf3ebeb83dc9,0xbf6abf80bf5fbf0e,0x3f273e79be60bf22,0x3f7c3f4e3ee60000,0xbdfb3eac3f393f75,
0x3f803f673f1d3e48,0xbea13e163f133f62,0xbf58bf04bd973ec4,0xbe89bf2cbf6fbf7f,0x3ecfbd49befcbf55,0x3f423f783f7a3f46,0x3e2f3f183f653f80,0xbf7ebf71bf31be95,
0x3dc93f0e3f623f80,0xbf75bf7bbf46bec4,0x3f223e48be95bf35,0x3ef13f553f7f3f6d,0xbf7fbf55bef10000,0x3e95be48bf22bf6d,0x3f463f7b3f753f35,0xbf62bf0ebdc93ec4,
0xbf7fbf55bef18000,0x3e95be48bf22bf6d,0x3f463f7b3f753f35,0xbf62bf0ebdc93ec4,0xbdc9bf0ebf62bf80,0x3f753f7b3f463ec4,0xbf22be483e953f35,0xbef1bf55bf7fbf6d,
0x3f133f673f7f3f55,0xbf7ebf4ebecf3dc9,0xbf80bf5cbefc0000,0x3ee6bd49bf09bf62,0xbf7abf3ebea13e48,0x3e89be79bf31bf75,0x3eb8be16bf1dbf6d,0x3f273f713f7c3f46,
0xbf51bedb3d973f0e,0xbdfbbf18bf6abf7f,0xbcc9bf04bf5fbf80,0x3f653f803f583ef1,0xbe60bf2cbf73bf7b,0x3f773f783f393e95,0x3f6f3f7d3f4a3ec4,0xbf42beac3e2f3f22,
0x3f2c3f753f783f35,0xbf7dbf46beac3e48,0x3edbbdc9bf18bf6d,0x3f043f623f803f55,0x3d49bef1bf5cbf80,0x3f4e3f7f3f673f0e,0xbf71bf22be163ec4,0x3e79be95bf3ebf7b,
0xbf3ebe953e793f35,0xbe16bf22bf71bf7b,0x3f673f7f3f4e3ec4,0xbf5cbef13d493f0e,0x3f803f623f048000,0xbf18bdc93edb3f55,0xbeacbf46bf7dbf6d,0x3f783f753f2c3e48,
0x3ee63f5c3f803f55,0xbf7abf71bf1dbdc9,0xbf77bf2cbe2f3ec4,0x3ecfbe16bf27bf75,0xbd97bf18bf6fbf7b,0x3f513f803f5f3ef1,0x3f7e3f673f090000,0xbf39be793ea13f46,
0xbf65bf043cc93f0e,0x3e60beacbf4abf7f,0xbe89bf3ebf7cbf6d,0x3f6a3f7d3f423e95,0x3f7f3f4e3eb8be48,0xbf13bd493efc3f62,0xbdfb3edb3f583f80,0xbf31bf78bf73bf22,
0xbe483ec43f553f80,0xbf0ebf6dbf7bbf35,0x3f7b3f6d3f0e0000,0xbf55bec43e483f35,0x3e48bec4bf55bf80,0x3f0e3f6d3f7b3f35,0xbf7bbf6dbf0e0000,0x3f553ec4be48bf35,
0xbf7bbf6dbf0e8000,0x3f553ec4be48bf35,0xbe483ec43f553f80,0xbf0ebf6dbf7bbf35,0x3f7b3f6d3f0e8000,0xbf55bec43e483f35,0x3e48bec4bf55bf80,0x3f0e3f6d3f7b3f35,
0xbee63e163f313f7b,0xbe60bf3ebf7ebf62,0xbf77bf71bf130000,0x3f6a3f04bd97bf22,0x3f423e79beb8bf55,0xbe2f3edb3f5f3f7f,0x3f4a3f803f583ec4,0xbf80bf4ebea13e95,
0xbf65bf7dbf39be48,0x3f7a3f2c3dfbbef1,0x3e89beacbf51bf80,0x3ecf3f5c3f7f3f46,0x3f273f783f6f3f0e,0xbf7cbf67befc3dc9,0xbf1dbd493f093f6d,0xbcc9bf18bf73bf75,
0xbf67bef13e163f35,0x3f04bdc9bf2cbf7b,0x3d493f223f783f6d,0xbf18bf75bf71bf0e,0x3eacbe95bf4ebf80,0x3e793f463f803f55,0xbf3ebf7fbf5cbec4,0x3f7d3f623edbbe48,
0xbedbbf62bf7dbf35,0x3f5c3f7f3f3e3e48,0xbf80bf46be793ec4,0x3f4e3e95beacbf55,0x3f713f753f188000,0xbf78bf22bd493f0e,0x3f2c3dc9bf04bf6d,0xbe163ef13f673f7b,
0xbf51bf80bf42be48,0x3f7e3f5c3eb8be95,0x3cc9bf18bf77bf6d,0x3ee63f673f7a3f22,0x3f583eacbea1bf55,0xbefc3e163f393f7f,0x3f6a3f783f1d0000,0xbf7fbf3ebe2f3ef1,
0x3f13bd49bf27bf7b,0xbdfb3f043f6f3f75,0x3f803f4e3e89bec4,0xbf65bedb3e603f46,0x3f093f713f733f0e,0xbf5fbf7dbf31bdc9,0xbecf3e793f4a3f80,0xbd97bf2cbf7cbf62,
0xbef13e483f463f80,0x3dc9bf0ebf75bf6d,0x3e953f553f7f3f35,0xbf22bf7bbf62bec4,0x3f623f7b3f220000,0xbf7fbf55be953ec4,0x3f753f0ebdc9bf35,0xbf46be483ef13f6d,
0xbf62bf7bbf228000,0x3f7f3f553e95bec4,0xbf75bf0e3dc93f35,0x3f463e48bef1bf6d,0xbef13e483f463f80,0x3dc9bf0ebf75bf6d,0x3e953f553f7f3f35,0xbf22bf7bbf62bec4,
0xbf80bf3ebdfb3f0e,0x3f733f04be2fbf46,0xbf58bf7dbf270000,0x3f773f673ecfbe95,0xbeb83eac3f5f3f7b,0x3d97bf18bf7abf62,0xbf51be793ee63f6d,0x3f1dbd49bf31bf7f,
0xbcc9bf2cbf7ebf55,0x3ea13f5c3f7c3f22,0x3f09be16bf42bf80,0xbe893edb3f6a3f75,0xbf6fbf71befc3e48,0x3f7f3f4e3e60bef1,0xbf13bf78bf65bec4,0x3f4a3f803f393dc9,
0xbe16bf46bf80bf35,0x3eac3f623f783f0e,0xbf04bf75bf67bec4,0x3f2c3f7f3f4e3e48,0x3f18bdc9bf3ebf80,0xbedb3e953f5c3f7b,0x3e79bef1bf71bf6d,0xbd493f223f7d3f55,
0x3f7d3f22bd49bf35,0xbf71bef13e793f55,0x3f5c3e95bedbbf6d,0xbf3ebdc93f183f7b,0x3f4e3f7f3f2c8000,0xbf67bf75bf043e48,0x3f783f623eacbec4,0xbf80bf46be163f0e,
0x3f7e3f4e3e2fbf0e,0xbf80bf3ebd973f22,0x3f733f673eb8bec4,0xbf7abf5cbe893ef1,0x3f5f3f783f09be48,0xbf6abf71bee63e95,0x3f423f803f310000,0xbf51bf7dbf1d3dc9,
0xbdfb3f183f7c3f55,0x3cc9bf2cbf7fbf46,0xbea13edb3f6f3f6d,0x3e60bf04bf77bf62,0xbefc3e793f583f7b,0x3ecfbeacbf65bf75,0xbf273d493f393f80,0x3f13be16bf4abf7f,
0x3f003f003f003f00,0x3f003f003f003f00,0x3f003f003f003f00,0x3f003f003f003f00,0x3f003f003f003f00,0x3f003f003f003f00,0x3f003f003f003f00,0x3f003f003f003f00,
0xbf003f00bf003f00,0xbf003f00bf003f00,0xbf003f00bf003f00,0xbf003f00bf003f00,0xbf003f00bf003f00,0xbf003f00bf003f00,0xbf003f00bf003f00,0xbf003f00bf003f00,
0xbf5fbf5cbf58bf55,0xbf6abf67bf65bf62,0xbf42bf3ebf39bf35,0xbf51bf4ebf4abf46,0xbf7ebf7dbf7cbf7b,0xbf80bf80bf7fbf7f,0xbf73bf71bf6fbf6d,0xbf7abf78bf77bf75,
0xbefcbf04bf09bf0e,0xbecfbedbbee6bef1,0xbf27bf2cbf31bf35,0xbf13bf18bf1dbf22,0xbdfbbe16be2fbe48,0xbcc9bd49bd97bdc9,0xbea1beacbeb8bec4,0xbe60be79be89be95,
0x3f4e3f463f3e3f35,0x3f673f623f5c3f55,0x3f783f753f713f6d,0x3f803f7f3f7d3f7b,0x3e163dc93d490000,0x3eac3e953e793e48,0x3f043ef13edb3ec4,0x3f2c3f223f183f0e,
0x3f183f223f2c3f35,0x3edb3ef13f043f0e,0x3e793e953eac3ec4,0x3d493dc93e163e48,0x3f7d3f7f3f803f80,0x3f713f753f783f7b,0x3f5c3f623f673f6d,0x3f3e3f463f4e3f55,
0xbf6fbf67bf5fbf55,0xbf7fbf7dbf7abf75,0xbf13bf04bee6bec4,0xbf4abf3ebf31bf22,0xbcc93d493dfb3e48,0xbea1be79be2fbdc9,0x3f093f183f273f35,0x3e893eac3ecf3ef1,
0xbeb8bedbbefcbf0e,0xbd97be16be60be95,0xbf51bf5cbf65bf6d,0xbf1dbf2cbf39bf46,0xbf80bf80bf7ebf7b,0xbf73bf78bf7cbf7f,0xbf58bf4ebf42bf35,0xbf77bf71bf6abf62,
0xbf75bf7bbf7fbf80,0xbf46bf55bf62bf6d,0xbef1bf0ebf22bf35,0xbdc9be48be95bec4,0x3e953e483dc90000,0x3f223f0e3ef13ec4,0x3f623f553f463f35,0x3f7f3f7b3f753f6d,
0x3e953e483dc98000,0x3f223f0e3ef13ec4,0x3f623f553f463f35,0x3f7f3f7b3f753f6d,0x3f753f7b3f7f3f80,0x3f463f553f623f6d,0x3ef13f0e3f223f35,0x3dc93e483e953ec4,
0x3f583f673f733f7b,0x3efc3f183f313f46,0x3f6a3f5c3f4a3f35,0x3f7f3f803f7c3f75,0xbf51bf3ebf27bf0e,0xbf7ebf78bf6fbf62,0x3cc93e163e893ec4,0xbee6beacbe60bdc9,
0xbf09bedbbea1be48,0xbf5fbf4ebf39bf22,0x3ecf3f043f1d3f35,0xbd973d493e2f3e95,0xbf13bf2cbf42bf55,0xbdfbbe79beb8bef1,0xbf80bf7dbf77bf6d,0xbf65bf71bf7abf7f,
0xbeacbef1bf18bf35,0x3e793dc9bd49be48,0x3f3e3f223f043ec4,0x3f7d3f753f673f55,0xbedbbe95be160000,0xbf5cbf46bf2cbf0e,0xbf80bf7fbf78bf6d,0xbf4ebf62bf71bf7b,
0x3f713f623f4e3f35,0x3f783f7f3f803f7b,0x3f2c3f463f5c3f6d,0x3e163e953edb3f0e,0xbf67bf75bf7dbf80,0xbf04bf22bf3ebf55,0x3d49bdc9be79bec4,0x3f183ef13eac3e48,
0xbf27bf04beb8be48,0xbf7cbf71bf5fbf46,0x3f1d3f3e3f583f6d,0xbcc93e163ea13ef1,0x3f653f4e3f313f0e,0x3f7a3f803f7e3f75,0xbe89bedbbf13bf35,0x3ecf3e793d97bdc9,
0xbf42bf5cbf6fbf7b,0xbe2fbeacbefcbf22,0xbf4abf2cbf09bec4,0xbf80bf7dbf73bf62,0x3ee63f183f393f55,0xbe60bd493dfb3e95,0x3f773f673f513f35,0x3f6a3f783f7f3f7f,
0x3f553f6d3f7b3f80,0x3e483ec43f0e3f35,0xbf0ebec4be480000,0xbf7bbf6dbf55bf35,0xbf55bf6dbf7bbf80,0xbe48bec4bf0ebf35,0x3f0e3ec43e480000,0x3f7b3f6d3f553f35,
0xbf0ebec4be488000,0xbf7bbf6dbf55bf35,0xbf55bf6dbf7bbf80,0xbe48bec4bf0ebf35,0x3f0e3ec43e488000,0x3f7b3f6d3f553f35,0x3f553f6d3f7b3f80,0x3e483ec43f0e3f35,
0x3d97be16beb8bf0e,0x3f513f2c3efc3e95,0xbf7ebf71bf58bf35,0xbf39bf5cbf73bf7f,0xbee6be79bcc93e48,0xbf7abf67bf4abf22,0x3f773f803f7c3f6d,0x3ecf3f183f423f62,
0x3f7f3f7d3f6f3f55,0x3f133f3e3f5f3f75,0xbdfbbeacbf09bf35,0x3f313f043ea13dc9,0xbf65bf78bf80bf7b,0xbe60bedbbf1dbf46,0xbe89bd493e2f3ec4,0xbf6abf4ebf27bef1,
0xbf80bf75bf5cbf35,0xbf18bf46bf67bf7b,0x3eac3dc9be16bec4,0x3f783f623f3e3f0e,0x3f2c3ef13e790000,0x3f7d3f7f3f713f55,0x3edb3f223f4e3f6d,0xbf04be95bd493e48,
0xbd49be95bf04bf35,0x3f4e3f223edb3e48,0x3f713f7f3f7d3f6d,0x3e793ef13f2c3f55,0x3f3e3f623f783f80,0xbe163dc93eac3f0e,0xbf67bf46bf18bec4,0xbf5cbf75bf80bf7b,
0xbe603d493ea13f0e,0xbf77bf5cbf31bef1,0x3f6f3f4e3f1d3ec4,0x3f423f673f7c3f7f,0xbf51bf71bf7fbf7b,0x3dfbbe16becfbf22,0xbcc93e793efc3f35,0xbf65bf3ebf09be95,
0xbf7abf80bf73bf55,0xbe89bf04bf39bf62,0x3eb83f183f4a3f6d,0xbf27bedbbe2f3dc9,0x3f133eac3d97be48,0x3f7e3f7d3f6a3f46,0xbf80bf78bf5fbf35,0xbee6bf2cbf58bf75,
0xbf22bf55bf75bf80,0x3ef13e48bdc9bec4,0x3f7f3f7b3f623f35,0x3e953f0e3f463f6d,0xbf46bf0ebe950000,0xbf62bf7bbf7fbf6d,0x3dc9be48bef1bf35,0x3f753f553f223ec4,
0x3f463f0e3e958000,0x3f623f7b3f7f3f6d,0xbdc93e483ef13f35,0xbf75bf55bf22bec4,0xbf22bf55bf75bf80,0x3ef13e48bdc9bec4,0x3f7f3f7b3f623f35,0x3e953f0e3f463f6d,
0xbf6abf3ebefcbe48,0xbf27bf5cbf7abf7f,0x3f7c3f7d3f653f35,0x3dfb3edb3f313f62,0x3cc93eac3f1d3f55,0xbf73bf4ebf13be95,0x3f093e79bd97bec4,0x3f773f803f6f3f46,
0xbecfbf2cbf5fbf7b,0x3f423f043e60bdc9,0xbe2f3e163ee63f35,0xbf7ebf67bf39bef1,0xbf80bf71bf4abf0e,0xbea1bf18bf51bf75,0x3f583f783f7f3f6d,0xbe893d493eb83f22,
0xbe793dc93edb3f35,0xbf80bf75bf4ebf0e,0xbe16bef1bf3ebf6d,0x3f713f463f043e48,0xbf5cbf22beac0000,0xbf2cbf62bf7dbf7b,0x3f183e95bd49bec4,0x3f673f7f3f783f55,
0xbf78bf7fbf67bf35,0x3d49be95bf18bf55,0x3f7d3f623f2c3ec4,0x3eac3f223f5c3f7b,0xbf04bf46bf71bf80,0x3f3e3ef13e16be48,0x3f4e3f753f803f6d,0xbedbbdc93e793f0e,
0x3e893f183f583f7b,0xbf6fbf3ebee6bdc9,0xbd97bedbbf39bf6d,0x3f7c3f5c3f1d3e95,0xbdfb3e793f133f55,0xbf80bf71bf42bef1,0x3ea1bd49becfbf35,0x3f7a3f7d3f5f3f22,
0xbf77bf4ebf09be48,0xbeb8bf2cbf65bf7f,0x3f7f3f673f313ec4,0x3e2f3f043f4a3f75,0xbf7ebf78bf51bf0e,0x3cc9beacbf27bf62,0x3f733f803f6a3f35,0xbe603e163efc3f46,
0x3ec43f353f6d3f80,0xbf6dbf35bec40000,0xbec4bf35bf6dbf80,0x3f6d3f353ec40000,0x3ec43f353f6d3f80,0xbf6dbf35bec40000,0xbec4bf35bf6dbf80,0x3f6d3f353ec40000,
0xbf6dbf35bec48000,0xbec4bf35bf6dbf80,0x3f6d3f353ec48000,0x3ec43f353f6d3f80,0xbf6dbf35bec48000,0xbec4bf35bf6dbf80,0x3f6d3f353ec48000,0x3ec43f353f6d3f80,
0x3f4a3f783f7c3f55,0xbf31beac3d973ef1,0xbf65bf80bf6fbf35,0x3f093e16be89bf22,0x3efc3f4e3f7a3f7b,0xbf6abf2cbea13dc9,0xbf27bf67bf80bf6d,0x3f513f043dfbbe95,
0xbf1dbe793e2f3f0e,0xbf39bf71bf7fbf62,0x3ee63d49beb8bf35,0x3f583f7d3f773f46,0xbf5fbf18be603e48,0xbecfbf3ebf73bf7f,0x3f423edb3cc9bec4,0x3f133f5c3f7e3f75,
0x3f5c3f7f3f713f35,0xbf2cbe953e163f0e,0xbf18bf62bf80bf6d,0x3f673f223e79be48,0x3f783f463edb0000,0x3d493ef13f4e3f7b,0xbf7dbf75bf3ebec4,0x3eacbdc9bf04bf55,
0xbf04bdc93eac3f35,0xbf3ebf75bf7dbf55,0x3f4e3ef13d49bec4,0x3edb3f463f783f7b,0x3e793f223f673f80,0xbf80bf62bf18be48,0x3e16be95bf2cbf6d,0x3f713f7f3f5c3f0e,
0x3f313f713f7e3f55,0xbf65bf18be2f3e95,0xbf7abf78bf42bec4,0x3efc3d49becfbf46,0x3f6f3f2c3e89be48,0x3d973f043f583f7f,0xbf13be163ea13f35,0xbf1dbf67bf80bf62,
0xbf39beac3dfb3f0e,0xbee6bf4ebf7cbf75,0x3e60be79bf27bf6d,0x3f5f3f803f6a3f22,0x3eb83f3e3f773f7b,0xbf7fbf5cbf09bdc9,0xbf51bf7dbf73bf35,0x3f4a3edbbcc9bef1,
0xbdc9bf0ebf62bf80,0x3f753f7b3f463ec4,0xbf22be483e953f35,0xbef1bf55bf7fbf6d,0x3f7f3f553ef10000,0xbe953e483f223f6d,0xbf46bf7bbf75bf35,0x3f623f0e3dc9bec4,
0x3f7f3f553ef18000,0xbe953e483f223f6d,0xbf46bf7bbf75bf35,0x3f623f0e3dc9bec4,0x3dc93f0e3f623f80,0xbf75bf7bbf46bec4,0x3f223e48be95bf35,0x3ef13f553f7f3f6d,
0x3e2fbeacbf42bf7b,0x3f4a3f7d3f6f3f22,0x3f393f783f773f35,0xbf73bf2cbe603e95,0x3f583f803f653f0e,0xbf5fbf04bcc93ef1,0xbf6abf18bdfb3ec4,0x3d97bedbbf51bf7f,
0x3f7c3f713f273e48,0xbf1dbe163eb83f46,0xbf31be793e893f35,0xbea1bf3ebf7abf75,0xbf09bd493ee63f55,0xbefcbf5cbf80bf62,0xbecfbf4ebf7ebf6d,0x3f7f3f673f133dc9,
0x3f3e3e95be79bf35,0x3e163f223f713f7b,0xbf67bf7fbf4ebec4,0x3f5c3ef1bd49bf0e,0xbf80bf62bf040000,0x3f183dc9bedbbf55,0x3eac3f463f7d3f6d,0xbf78bf75bf2cbe48,
0x3f2c3f753f783f35,0xbf7dbf46beac3e48,0x3edbbdc9bf18bf6d,0x3f043f623f803f55,0x3d49bef1bf5cbf80,0x3f4e3f7f3f673f0e,0xbf71bf22be163ec4,0x3e79be95bf3ebf7b,
0x3f733f783f313e48,0xbf58bedb3dfb3f22,0xbefc3d493f133f6d,0xbeb8bf4ebf7fbf62,0xbf42bf7dbf6abf0e,0x3f7c3f3e3e89be95,0x3f4a3eacbe60bf35,0xbcc93f043f653f7f,
0xbea13e793f393f7b,0xbf09bf67bf7ebf46,0xbf5fbf80bf51bec4,0x3f6f3f183d97bef1,0x3f273e16becfbf55,0x3e2f3f2c3f773f75,0x3f1d3f713f7a3f35,0xbf80bf5cbee63dc9,
0xbe483ec43f553f80,0xbf0ebf6dbf7bbf35,0x3f7b3f6d3f0e0000,0xbf55bec43e483f35,0x3e48bec4bf55bf80,0x3f0e3f6d3f7b3f35,0xbf7bbf6dbf0e0000,0x3f553ec4be48bf35,
0xbf7bbf6dbf0e8000,0x3f553ec4be48bf35,0xbe483ec43f553f80,0xbf0ebf6dbf7bbf35,0x3f7b3f6d3f0e8000,0xbf55bec43e483f35,0x3e48bec4bf55bf80,0x3f0e3f6d3f7b3f35,
0xbf73bf18bcc93f0e,0x3f09bd49bf1dbf75,0xbefcbf67bf7cbf35,0x3f6f3f783f273dc9,0x3f7f3f5c3ecfbe48,0xbf51beac3e893f46,0x3dfb3f2c3f7a3f6d,0xbf39bf7dbf65bef1,
0xbea1bf4ebf80bf55,0x3f583f803f4a3e95,0x3f5f3edbbe2fbf35,0xbeb83e793f423f7f,0xbd973f043f6a3f7b,0xbf13bf71bf77bf22,0xbf7ebf3ebe603ec4,0x3f313e16bee6bf62,
0xbedbbf62bf7dbf35,0x3f5c3f7f3f3e3e48,0xbf80bf46be793ec4,0x3f4e3e95beacbf55,0x3f713f753f180000,0xbf78bf22bd493f0e,0x3f2c3dc9bf04bf6d,0xbe163ef13f673f7b,
0x3f673ef1be16bf35,0xbf043dc93f2c3f7b,0xbd49bf22bf78bf6d,0x3f183f753f713f0e,0xbeac3e953f4e3f80,0xbe79bf46bf80bf55,0x3f3e3f7f3f5c3ec4,0xbf7dbf62bedb3e48,
0x3f7c3f2c3d97bf0e,0xbf4abe793ecf3f62,0x3f313f7d3f5f3ec4,0xbf73bf71bf093dc9,0xbe603edb3f653f7b,0xbe89bf4ebf80bf46,0xbf6fbf043dfb3f35,0x3f273d49bf13bf75,
0x3e2f3f3e3f7f3f55,0xbf1dbf78bf6abef1,0xbf39be163efc3f6d,0x3ea1beacbf58bf7f,0xbf7abf67bee63e48,0x3f773f18bcc9bf22,0xbeb8bf5cbf7ebf35,0x3f423f803f513e95,
0x3ef1be48bf46bf80,0xbdc93f0e3f753f6d,0xbe95bf55bf7fbf35,0x3f223f7b3f623ec4,0xbf62bf7bbf220000,0x3f7f3f553e95bec4,0xbf75bf0e3dc93f35,0x3f463e48bef1bf6d,
0x3f623f7b3f228000,0xbf7fbf55be953ec4,0x3f753f0ebdc9bf35,0xbf46be483ef13f6d,0x3ef1be48bf46bf80,0xbdc93f0e3f753f6d,0xbe95bf55bf7fbf35,0x3f223f7b3f623ec4,
0x3f393f803f4a3e48,0xbf65bf78bf133dc9,0x3e603f4e3f7f3f35,0xbefcbf71bf6fbef1,0x3f6a3edbbe89bf55,0xbf42be163f093f75,0x3f7c3f5c3ea1bec4,0xbf7ebf2cbcc93f22,
0xbf31bd493f1d3f7b,0x3ee6be79bf51bf7f,0xbf7abf183d973f35,0x3f5f3eacbeb8bf62,0x3ecf3f673f773f0e,0xbf27bf7dbf58be95,0xbe2f3f043f733f6d,0xbdfbbf3ebf80bf46,
0xbf7dbf223d493f35,0x3f713ef1be79bf55,0xbf5cbe953edb3f6d,0x3f3e3dc9bf18bf7b,0xbf4ebf7fbf2c0000,0x3f673f753f04be48,0xbf78bf62beac3ec4,0x3f803f463e16bf0e,
0xbe16bf46bf80bf35,0x3eac3f623f783f0e,0xbf04bf75bf67bec4,0x3f2c3f7f3f4e3e48,0x3f18bdc9bf3ebf80,0xbedb3e953f5c3f7b,0x3e79bef1bf71bf6d,0xbd493f223f7d3f55,
0x3f4a3e16bf13bf7b,0xbf39bd493f273f7f,0x3f653eacbecfbf6d,0xbf58be793efc3f75,0x3f773f04be60bf55,0xbf6fbedb3ea13f62,0x3f7f3f2cbcc9bf35,0xbf7cbf183dfb3f46,
0x3f1d3f7d3f513e48,0xbf31bf80bf42bdc9,0x3ee63f713f6a3ec4,0xbf09bf78bf5fbe95,0x3e893f5c3f7a3f0e,0xbeb8bf67bf73bef1,0x3d973f3e3f803f35,0xbe2fbf4ebf7ebf22,
0xbf8000003f80,0xbf8000003f80,0xbf8000003f80,0xbf8000003f80,0xbf8000003f80,0xbf8000003f80,0xbf8000003f80,0xbf8000003f80,
0x3f808000bf808000,0x3f808000bf808000,0x3f808000bf808000,0x3f808000bf808000,0x3f808000bf808000,0x3f808000bf808000,0x3f808000bf808000,0x3f808000bf808000,
0x3f773e79bf7abe48,0x3f6f3eacbf73be95,0x3f7f3d49bf800000,0x3f7c3e16bf7ebdc9,0x3f4a3f18bf51bf0e,0x3f393f2cbf42bf22,0x3f653edbbf6abec4,0x3f583f04bf5fbef1,
0xbe893f783e60bf7b,0xbeb83f713ea1bf75,0xbd973f803cc9bf80,0xbe2f3f7d3dfbbf7f,0xbf1d3f4e3f13bf55,0xbf313f3e3f27bf46,0xbee63f673ecfbf6d,0xbf093f5c3efcbf62,
0xbf4e3f223f3ebf35,0xbf673ef13f5cbf0e,0xbf783e953f71bec4,0xbf803dc93f7dbe48,0xbe163f7f3d49bf80,0xbeac3f753e79bf7b,0xbf043f623edbbf6d,0xbf2c3f463f18bf55,
0xbf18bf463f2c3f35,0xbedbbf623f043f55,0xbe79bf753eac3f6d,0xbd49bf7f3e163f7b,0xbf7dbdc93f808000,0xbf71be953f783e48,0xbf5cbef13f673ec4,0xbf3ebf223f4e3f0e,
0x3ecfbf71be893f7b,0x3f27bf4ebf093f62,0xbe2fbf783ea13f6d,0x3dfbbf803cc93f7f,0xbf31bf2c3f4a3f0e,0xbee6bf5c3f133f46,0xbf7abe163f7f0000,0xbf5fbedb3f6f3e95,
0x3f6a3eacbf77be48,0x3f423f18bf58bef1,0x3f7cbe79bf733ec4,0x3f7e3d49bf803dc9,0x3f39bf3ebf1d3f55,0x3f65bf04bf513f22,0x3e60bf7dbd973f80,0x3efcbf67beb83f75,
0x3e95bf7bbdc93f80,0x3f22bf55bef13f6d,0x3f62bf0ebf463f35,0x3f7fbe48bf753ec4,0x3f753e48bf7f0000,0x3f463f0ebf62bec4,0x3ef13f55bf22bf35,0x3dc93f7bbe95bf6d,
0x3f753e48bf7f8000,0x3f463f0ebf62bec4,0x3ef13f55bf22bf35,0x3dc93f7bbe95bf6d,0xbe953f7b3dc9bf80,0xbf223f553ef1bf6d,0xbf623f0e3f46bf35,0xbf7f3e483f75bec4,
0x3e603f71bee6bf55,0xbe893f7d3cc9bf7f,0x3f6f3e79bf7e0000,0x3f273f2cbf51bef1,0xbf7cbd493f7fbe48,0xbf4abf043f6a3e95,0xbf313f4e3efcbf6d,0xbf733edb3f58bf22,
0xbf7a3eac3f65bf0e,0xbf77be163f80bdc9,0xbeb83f783dfbbf80,0xbf423f3e3f13bf62,0x3e2fbf803d973f7b,0x3f1dbf5cbecf3f75,0xbf39bf183f5f3ec4,0xbea1bf673f093f46,
0xbeacbf623f183f35,0x3e79bf7f3d493f7b,0x3f3ebf46bf043f6d,0x3f7dbe95bf673f0e,0xbedb3f753e16bf80,0xbf5c3f223f2cbf55,0xbf803dc93f78bec4,0xbf4ebef13f713e48,
0x3f71bef1bf4e3f35,0x3f783dc9bf803e48,0x3f2c3f22bf5cbec4,0x3e163f75bedbbf55,0xbf67be953f7d8000,0xbf04bf463f3e3f0e,0x3d49bf7f3e793f6d,0x3f18bf62beac3f7b,
0x3d973f78becfbf55,0xbf133f673e89bf7f,0x3f7ebd49bf7a3ec4,0x3f313f18bf65be95,0x3ea1bf7d3cc93f7b,0x3f58bf2cbf1d3f62,0xbf5fbeac3f7c0000,0xbeb8bf5c3f273f22,
0xbf7f3e793f6abf0e,0xbf51bedb3f773dc9,0xbdfb3f80be60bf6d,0xbf393f4e3ee6bf75,0x3f733e16bf803e48,0x3f093f3ebf4abef1,0x3efcbf71be2f3f80,0x3f6fbf04bf423f46,
0x3f0ebf6dbe483f80,0x3f7bbec4bf553f35,0x3f553ec4bf7b0000,0x3e483f6dbf0ebf35,0xbf0e3f6d3e48bf80,0xbf7b3ec43f55bf35,0xbf55bec43f7b0000,0xbe48bf6d3f0e3f35,
0x3f553ec4bf7b8000,0x3e483f6dbf0ebf35,0xbf0e3f6d3e48bf80,0xbf7b3ec43f55bf35,0xbf55bec43f7b8000,0xbe48bf6d3f0e3f35,0x3f0ebf6dbe483f80,0x3f7bbec4bf553f35,
0xbf423f4e3ecfbf7b,0xbf7c3d493f77bef1,0x3f4a3edbbf7a0000,0x3cc93f78bee6bf46,0x3f73bf04bf393f55,0x3f583eacbf7e3dc9,0xbefcbf3e3f513ec4,0x3eb8bf7d3d973f75,
0xbf27bf183f6a3e48,0x3e2fbf803e893f62,0xbf1d3f673e60bf80,0xbf803e793f65bf22,0x3ea13f5cbf31bf0e,0xbf093f713dfbbf7f,0x3f5fbf2cbf133f6d,0x3f6f3e16bf7f3e95,
0x3f80be95bf5c3f35,0x3f183f22bf67be48,0xbeac3f7fbe16bf6d,0xbf783ef13f3ebf55,0xbf2c3f623e79bf80,0xbf7d3dc93f71bf0e,0xbedbbf463f4e3ec4,0x3f04bf75bd493f7b,
0x3d493f75bf04bf35,0xbf4e3f463edbbf7b,0xbf71bdc93f7dbec4,0xbe79bf623f2c3f0e,0xbf3ebef13f788000,0x3e16bf7f3eac3f55,0x3f67bf22bf183f6d,0x3f5c3e95bf803e48,
0xbf09bf2c3f653e48,0x3efcbf783cc93f75,0xbecf3f7dbdfbbf6d,0xbf7f3eac3f51bf46,0x3f7cbedbbf423f55,0x3f1d3f18bf6fbdc9,0xbf31bf043f770000,0x3ea1bf803e603f62,
0x3f58bf3ebee63f7b,0x3f5f3e79bf803e95,0xbf6abe163f7ebec4,0xbd97bf713f133f22,0x3e2f3f67bf27bf0e,0xbf4a3f4e3eb8bf7f,0x3f39bf5cbe893f80,0x3f733d49bf7a3ef1,
0x3f46bf55be953f80,0x3f623e48bf7f3ec4,0xbdc93f7bbef1bf35,0xbf753f0e3f22bf6d,0xbf22bf0e3f750000,0x3ef1bf7b3dc93f6d,0x3f7fbe48bf623f35,0x3e953f55bf46bec4,
0x3f223f0ebf758000,0xbef13f7bbdc9bf6d,0xbf7f3e483f62bf35,0xbe95bf553f463ec4,0x3f46bf55be953f80,0x3f623e48bf7f3ec4,0xbdc93f7bbef1bf35,0xbf753f0e3f22bf6d,
0xbf6fbd493f77bf0e,0x3d97bf783f093f22,0x3f133f18bf730000,0xbf1d3f713cc9bf75,0xbf313f673dfbbf7b,0xbf65be163f7cbef1,0x3f7abf04bf273f6d,0x3efc3f2cbf6abdc9,
0x3eb8bf803e893f55,0x3f7fbe79bf583f46,0xbf513f4e3ea1bf80,0xbf4abeac3f80be95,0xbf39bedb3f7ebe48,0x3ee6bf7d3e2f3f62,0x3e603f5cbf42bec4,0xbf5f3f3e3ecfbf7f,
0xbe793f7fbedbbf35,0xbf803e953f4ebf55,0xbe16bf623f3e3ec4,0x3f71bf22bf043f7b,0xbf5c3f463eacbf80,0xbf2cbef13f7dbe48,0x3f18bf753d493f6d,0x3f673dc9bf783f0e,
0xbf783dc93f67bf35,0x3d49bf753f183f0e,0x3f7dbef1bf2c3f6d,0x3eac3f46bf5cbe48,0xbf04bf223f718000,0x3f3ebf62be163f7b,0x3f4e3e95bf803ec4,0xbedb3f7fbe79bf55,
0x3f5f3e16bf7a3f0e,0xbecf3f80bea1bf46,0xbf42beac3f80bec4,0x3f13bf783dfb3f62,0x3f1d3f04bf7c3e48,0xbf393f673d97bf75,0xbee6bf2c3f6f0000,0x3f58bf4ebe893f7f,
0xbefc3f7dbe60bf55,0xbf6abd493f73bf22,0x3f27bf713cc93f6d,0x3f513e79bf7e3ef1,0xbf4a3f5c3e2fbf7b,0xbf31bedb3f7fbe95,0x3f65bf3ebeb83f80,0x3f093f18bf773dc9,
0x3f6dbf35bec43f80,0x3ec43f35bf6d0000,0xbf6d3f353ec4bf80,0xbec4bf353f6d0000,0x3f6dbf35bec43f80,0x3ec43f35bf6d0000,0xbf6d3f353ec4bf80,0xbec4bf353f6d0000,
0x3ec43f35bf6d8000,0xbf6d3f353ec4bf80,0xbec4bf353f6d8000,0x3f6dbf35bec43f80,0x3ec43f35bf6d8000,0xbf6d3f353ec4bf80,0xbec4bf353f6d8000,0x3f6dbf35bec43f80,
0xbdfbbf5c3f513e48,0x3f80bedbbf273f75,0x3ea13f3ebf6a0000,0xbf7a3f183efcbf7f,0x3e89bf7d3f093f0e,0x3f6fbd49bf653f46,0xbd973f71bf31bec4,0xbf7c3e793f4abf62,
0x3f7ebf04bf133f7b,0x3cc93f67bf42be95,0xbf733f2c3ecfbf80,0xbe60bf4e3f5f3dc9,0x3f77be16bf583f55,0xbeb83f80bee6bf22,0xbf7f3eac3f39bf6d,0x3e2fbf783f1d3ef1,
0xbf5cbdc93f71bf35,0x3f2cbf753e163f55,0x3f183ef1bf803ec4,0xbf673f463e79bf7b,0xbf783f223edbbf80,0xbd49bf623f4e3e48,0x3f7dbe95bf3e3f6d,0xbeac3f7fbf04bf0e,
0x3f04bf7f3eac3f35,0x3f3e3e95bf7d3f0e,0xbf4e3f623d49bf6d,0xbedbbf223f78be48,0xbe79bf463f678000,0x3f80bef1bf183f7b,0xbe163f75bf2cbec4,0xbf713dc93f5cbf55,
0xbf803edb3f1dbf7b,0x3ea1bf7d3f133ef1,0x3f58bf5cbd973f6d,0x3e893f3ebf6f3dc9,0xbecf3f80befcbf0e,0xbf42be793f7abf22,0xbe2fbf4e3f650000,0x3f7ebeacbf313f75,
0x3cc9bf673f4a3e48,0x3f73be16bf513f62,0x3f093f04bf7f3ec4,0xbf773f2c3eb8bf7f,0xbf6a3d493f5fbf55,0x3f27bf783e603f46,0x3f7cbf18bee63f80,0xbdfb3f71bf39be95,
0x3f7fbf0ebef13f80,0xbe953f7bbf22bec4,0xbf46be483f75bf35,0x3f62bf55bdc93f6d,0x3dc93f55bf620000,0xbf753e483f46bf6d,0x3f22bf7b3e953f35,0x3ef13f0ebf7f3ec4,
0x3dc93f55bf628000,0xbf753e483f46bf6d,0x3f22bf7b3e953f35,0x3ef13f0ebf7f3ec4,0xbf7f3f0e3ef1bf80,0x3e95bf7b3f223ec4,0x3f463e48bf753f35,0xbf623f553dc9bf6d,
0x3f51bf673d973f55,0x3dfb3f4ebf6a3dc9,0x3cc93f5cbf5f0000,0xbf653d493f58bf62,0x3e603f3ebf733e48,0xbf773e793f39bf75,0xbf6f3e163f4abf6d,0x3f42bf713e2f3f46,
0x3f133edbbf7f3f0e,0xbf7e3f183ecfbf7f,0xbf803f043efcbf80,0x3ee6bf803f093ef1,0xbf7a3f2c3ea1bf7b,0x3e89bf783f313e95,0x3eb8bf7d3f1d3ec4,0x3f273eacbf7c3f22,
0x3f3ebf753e793f35,0x3e163f46bf713e48,0xbf673dc93f4ebf6d,0x3f5cbf623d493f55,0xbf803ef13f04bf80,0x3f18bf7f3edb3f0e,0x3eac3f22bf7d3ec4,0xbf783e953f2cbf7b,
0x3f2c3e95bf783f35,0xbf7d3f223eacbf7b,0x3edbbf7f3f183ec4,0x3f043ef1bf803f0e,0x3d49bf623f5c8000,0x3f4e3dc9bf673f55,0xbf713f463e16bf6d,0x3e79bf753f3e3e48,
0x3f65bf5c3cc93f55,0xbe603f71bf4abdc9,0x3e893f2cbf7c3ec4,0xbf6a3e163f42bf75,0xbf7f3f183eb8bf7b,0x3f13bf803efc3ef1,0x3dfbbf673f580000,0x3f313e79bf733f46,
0x3ee63f04bf803f0e,0xbf7a3eac3f1dbf7f,0xbf773f3e3e2fbf6d,0x3ecfbf7d3f273e95,0xbd97bf4e3f6fbe48,0x3f513d49bf5f3f62,0x3f7ebedbbf093f80,0xbf393f78bea1bf22,
0x3f7bbec4bf0e3f80,0xbf553f6dbe48bf35,0x3e48bf6d3f550000,0x3f0e3ec4bf7b3f35,0xbf7b3ec43f0ebf80,0x3f55bf6d3e483f35,0xbe483f6dbf550000,0xbf0ebec43f7bbf35,
0xbe483f6dbf558000,0xbf0ebec43f7bbf35,0x3f7bbec4bf0e3f80,0xbf553f6dbe48bf35,0x3e48bf6d3f558000,0x3f0e3ec4bf7b3f35,0xbf7b3ec43f0ebf80,0x3f55bf6d3e483f35,
0x3f65be16bf393f7b,0xbf7a3f3e3dfbbf62,0xbe893f71bf510000,0xbecfbf043f7fbf22,0xbf27be793f6fbf55,0x3f7cbedbbefc3f7f,0x3f1dbf803f093ec4,0x3cc93f4ebf733e95,
0xbee63f7dbf31be48,0xbe60bf2c3f7ebef1,0xbf773eac3f13bf80,0x3f6abf5c3d973f46,0x3f42bf783eb83f0e,0xbe2f3f67bf5f3dc9,0x3f4a3d49bf583f6d,0xbf803f183ea1bf75,
0x3edb3ef1bf7d3f35,0xbf5c3dc93f3ebf7b,0x3f80bf22be793f6d,0xbf4e3f75beacbf0e,0xbf713e953f18bf80,0x3f78bf46bd493f55,0xbf2c3f7fbf04bec4,0x3e16bf623f67be48,
0xbf673f62be16bf35,0x3f04bf7f3f2c3e48,0x3d493f46bf783ec4,0xbf18be953f71bf55,0x3eacbf753f4e8000,0x3e793f22bf803f0e,0xbf3ebdc93f5cbf6d,0x3f7dbef1bedb3f7b,
0xbf133f80bf27be48,0x3dfbbf5c3f6fbe95,0xbf803f183e89bf6d,0x3f65bf673e603f22,0xbf09beac3f73bf55,0x3f5fbe16bf313f7f,0x3ecfbf783f4a0000,0x3d973f3ebf7c3ef1,
0xbf513d493f42bf7b,0x3f7ebf04beb83f75,0x3cc9bf4e3f77bec4,0x3ee63edbbf7a3f46,0x3f58bf713ea13f0e,0xbefc3f7dbf39bdc9,0x3f6abe79bf1d3f80,0xbf7f3f2c3e2fbf62,
0x3f62be48bf223f80,0xbf7f3f0e3e95bf6d,0x3f75bf553dc93f35,0xbf463f7bbef1bec4,0x3ef1bf7b3f460000,0xbdc93f55bf753ec4,0xbe95bf0e3f7fbf35,0x3f223e48bf623f6d,
0xbef13f7bbf468000,0x3dc9bf553f75bec4,0x3e953f0ebf7f3f35,0xbf22be483f62bf6d,0x3f62be48bf223f80,0xbf7f3f0e3e95bf6d,0x3f75bf553dc93f35,0xbf463f7bbef1bec4,
0x3cc93f3ebf7e3f0e,0xbea1bf043f7cbf46,0xbf093f7dbf420000,0x3e89bf673f6abe95,0x3f6fbeacbefc3f7b,0xbf7f3f183e60bf62,0x3f133e79bf653f6d,0xbf4a3d493f39bf7f,
0xbf803f2c3dfbbf55,0x3f73bf5c3e2f3f22,0xbf583e163f27bf80,0x3f77bedbbecf3f75,0xbeb83f71bf5f3e48,0x3d97bf4e3f7abef1,0xbf513f78bee6bec4,0x3f1dbf803f313dc9,
0xbf7d3f46bd49bf35,0x3f71bf623e793f0e,0xbf5c3f75bedbbec4,0x3f3ebf7f3f183e48,0xbf4e3dc93f2cbf80,0x3f67be95bf043f7b,0xbf783ef13eacbf6d,0x3f80bf22be163f55,
0xbe16bf223f80bf35,0x3eac3ef1bf783f55,0xbf04be953f67bf6d,0x3f2c3dc9bf4e3f7b,0x3f18bf7f3f3e8000,0xbedb3f75bf5c3e48,0x3e79bf623f71bec4,0xbd493f46bf7d3f0e,
0x3dfbbf4e3f7cbf0e,0xbcc93f3ebf7f3f22,0x3ea1bf673f6fbec4,0xbe603f5cbf773ef1,0x3efcbf783f58be48,0xbecf3f71bf653e95,0x3f27bf803f390000,0xbf133f7dbf4a3dc9,
0x3f7ebf18be2f3f55,0xbf803f2c3d97bf46,0x3f73bedbbeb83f6d,0xbf7a3f043e89bf62,0x3f5fbe79bf093f7b,0xbf6a3eac3ee6bf75,0x3f42bd49bf313f80,0xbf513e163f1dbf7f,
0xbf8000003f80,0xbf8000003f80,0xbf8000003f80,0xbf8000003f80,0xbf8000003f80,0xbf8000003f80,0xbf8000003f80,0xbf8000003f80,
0x3f808000bf808000,0x3f808000bf808000,0x3f808000bf808000,0x3f808000bf808000,0x3f808000bf808000,0x3f808000bf808000,0x3f808000bf808000,0x3f808000bf808000,
0x3efc3f5cbf09bf55,0x3ecf3f67bee6bf62,0x3f273f3ebf31bf35,0x3f133f4ebf1dbf46,0x3dfb3f7dbe2fbf7b,0x3cc93f80bd97bf7f,0x3ea13f71beb8bf6d,0x3e603f78be89bf75,
0xbf5f3f043f58bf0e,0xbf6a3edb3f65bef1,0xbf423f2c3f39bf35,0xbf513f183f4abf22,0xbf7e3e163f7cbe48,0xbf803d493f7fbdc9,0xbf733eac3f6fbec4,0xbf7a3e793f77be95,
0xbf18bf463f2c3f35,0xbedbbf623f043f55,0xbe79bf753eac3f6d,0xbd49bf7f3e163f7b,0xbf7dbdc93f800000,0xbf71be953f783e48,0xbf5cbef13f673ec4,0xbf3ebf223f4e3f0e,
0x3f4ebf22bf3e3f35,0x3f67bef1bf5c3f0e,0x3f78be95bf713ec4,0x3f80bdc9bf7d3e48,0x3e16bf7fbd493f80,0x3eacbf75be793f7b,0x3f04bf62bedb3f6d,0x3f2cbf46bf183f55,
0x3eb83f67befcbf55,0x3d973f7dbe60bf75,0x3f513f04bf65bec4,0x3f1d3f3ebf39bf22,0x3f80bd49bf7e3e48,0x3f733e79bf7cbdc9,0x3f58bf18bf423f35,0x3f77beacbf6a3ef1,
0xbf6f3edb3f5fbf0e,0xbf7f3e163f7abe95,0xbf133f5c3ee6bf6d,0xbf4a3f2c3f31bf46,0xbcc93f80bdfbbf7b,0xbea13f783e2fbf7f,0x3f093f4ebf27bf35,0x3e893f71becfbf62,
0xbe953f7b3dc9bf80,0xbf223f553ef1bf6d,0xbf623f0e3f46bf35,0xbf7f3e483f75bec4,0xbf75be483f7f0000,0xbf46bf0e3f623ec4,0xbef1bf553f223f35,0xbdc9bf7b3e953f6d,
0xbf75be483f7f8000,0xbf46bf0e3f623ec4,0xbef1bf553f223f35,0xbdc9bf7b3e953f6d,0x3e95bf7bbdc93f80,0x3f22bf55bef13f6d,0x3f62bf0ebf463f35,0x3f7fbe48bf753ec4,
0x3f09bf67bea13f7b,0x3f5fbf18bf393f46,0xbecfbf5c3f1d3f35,0x3d97bf803e2f3f75,0x3f133f3ebf42bf0e,0x3dfb3f78beb8bf62,0x3f80be16bf773ec4,0x3f653eacbf7abdc9,
0x3f583edbbf73be48,0x3efc3f4ebf31bf22,0x3f6abf04bf4a3f35,0x3f7fbd49bf7c3e95,0xbf513f2c3f27bf55,0xbf7e3e793f6fbef1,0x3cc93f7dbe89bf6d,0xbee63f713e60bf7f,
0xbf713ef13f4ebf35,0xbf78bdc93f80be48,0xbf2cbf223f5c3ec4,0xbe16bf753edb3f55,0x3f673e95bf7d0000,0x3f043f46bf3ebf0e,0xbd493f7fbe79bf6d,0xbf183f623eacbf7b,
0xbeacbf623f183f35,0x3e79bf7f3d493f7b,0x3f3ebf46bf043f6d,0x3f7dbe95bf673f0e,0xbedb3f753e16bf80,0xbf5c3f223f2cbf55,0xbf803dc93f78bec4,0xbf4ebef13f713e48,
0x3f423f04bf6fbe48,0x3e2f3f71befcbf46,0x3f4abf3ebf093f6d,0x3f80be16bf733ef1,0xbee6bf4e3f393f0e,0x3e60bf803dfb3f75,0xbf773edb3f51bf35,0xbf6abe793f7fbdc9,
0xbf273f5c3eb8bf7b,0xbf7c3eac3f5fbf22,0x3f1d3f2cbf58bec4,0xbcc93f7dbea1bf62,0x3f65bf18bf313f55,0x3f7a3d49bf7e3e95,0xbe89bf673f133f35,0x3ecfbf78bd973f7f,
0x3f0ebf6dbe483f80,0x3f7bbec4bf553f35,0x3f553ec4bf7b0000,0x3e483f6dbf0ebf35,0xbf0e3f6d3e48bf80,0xbf7b3ec43f55bf35,0xbf55bec43f7b0000,0xbe48bf6d3f0e3f35,
0x3f553ec4bf7b8000,0x3e483f6dbf0ebf35,0xbf0e3f6d3e48bf80,0xbf7b3ec43f55bf35,0xbf55bec43f7b8000,0xbe48bf6d3f0e3f35,0x3f0ebf6dbe483f80,0x3f7bbec4bf553f35,
0xbf7f3e163f6fbf0e,0xbf13bf2c3f5f3e95,0x3dfb3f71bf09bf35,0xbf313f5c3ea1bf7f,0x3f653e79bf803e48,0x3e603f67bf1dbf22,0x3e89bf803e2f3f6d,0x3f6abf18bf273f62,
0x3d97bf7d3eb83f55,0x3f51bf3ebefc3f75,0xbf7e3eac3f58bf35,0xbf39bf043f733dc9,0xbee63f783cc9bf7b,0xbf7a3edb3f4abf46,0x3f773d49bf7c3ec4,0x3ecf3f4ebf42bef1,
0x3d493f75bf04bf35,0xbf4e3f463edbbf7b,0xbf71bdc93f7dbec4,0xbe79bf623f2c3f0e,0xbf3ebef13f780000,0x3e16bf7f3eac3f55,0x3f67bf22bf183f6d,0x3f5c3e95bf803e48,
0xbf803e953f5cbf35,0xbf18bf223f673e48,0x3eacbf7f3e163f6d,0x3f78bef1bf3e3f55,0x3f2cbf62be793f80,0x3f7dbdc9bf713f0e,0x3edb3f46bf4ebec4,0xbf043f753d49bf7b,
0x3f7abd49bf733f0e,0x3e893f5cbf39bef1,0xbeb8bf4e3f4a3ec4,0x3f27bf67be2f3f7f,0xbf133f713d97bf7b,0xbf7e3e163f6abf22,0x3f80be79bf5f3f35,0x3ee63f3ebf58be95,
0xbe603f80bea1bf55,0xbf773f043f31bf62,0x3f6fbf18bf1d3f6d,0x3f423edbbf7c3dc9,0xbf51beac3f7fbe48,0x3dfbbf7d3ecf3f46,0xbcc93f78befcbf35,0xbf653f2c3f09bf75,
0xbf463f553e95bf80,0xbf62be483f7fbec4,0x3dc9bf7b3ef13f35,0x3f75bf0ebf223f6d,0x3f223f0ebf750000,0xbef13f7bbdc9bf6d,0xbf7f3e483f62bf35,0xbe95bf553f463ec4,
0xbf22bf0e3f758000,0x3ef1bf7b3dc93f6d,0x3f7fbe48bf623f35,0x3e953f55bf46bec4,0xbf463f553e95bf80,0xbf62be483f7fbec4,0x3dc9bf7b3ef13f35,0x3f75bf0ebf223f6d,
0x3ecf3f3ebf5fbe48,0xbf423f5c3e60bf7f,0x3e2fbf7d3ee63f35,0x3f7ebedbbf393f62,0x3f80beacbf4a3f55,0x3ea13f4ebf51be95,0xbf58be793f7fbec4,0x3e89bf803eb83f46,
0xbf6a3f2c3efcbf7b,0xbf27bf043f7abdc9,0x3f7cbe16bf653f35,0x3dfb3f67bf31bef1,0x3cc93f71bf1dbf0e,0xbf733f183f13bf75,0x3f09bf783d973f6d,0x3f77bd49bf6f3f22,
0x3f78bdc9bf673f35,0xbd493f75bf18bf0e,0xbf7d3ef13f2cbf6d,0xbeacbf463f5c3e48,0x3f043f22bf710000,0xbf3e3f623e16bf7b,0xbf4ebe953f80bec4,0x3edbbf7f3e793f55,
0xbe793f7fbedbbf35,0xbf803e953f4ebf55,0xbe16bf623f3e3ec4,0x3f71bf22bf043f7b,0xbf5c3f463eacbf80,0xbf2cbef13f7dbe48,0x3f18bf753d493f6d,0x3f673dc9bf783f0e,
0x3f77bf18bf093f7b,0x3eb83f3ebf65bdc9,0xbf7f3edb3f31bf6d,0xbe2fbf5c3f4a3e95,0x3f7ebe79bf513f55,0xbcc93f71bf27bef1,0xbf733d493f6abf35,0x3e60bf7d3efc3f22,
0x3e893f4ebf58be48,0xbf6f3f2c3ee6bf7f,0xbd97bf673f393ec4,0x3f7cbf04bf1d3f75,0xbdfb3f78bf13bf0e,0xbf803eac3f42bf62,0x3ea1bf803ecf3f35,0x3f7abe16bf5f3f46,
0x3f6dbf35bec43f80,0x3ec43f35bf6d0000,0xbf6d3f353ec4bf80,0xbec4bf353f6d0000,0x3f6dbf35bec43f80,0x3ec43f35bf6d0000,0xbf6d3f353ec4bf80,0xbec4bf353f6d0000,
0x3ec43f35bf6d8000,0xbf6d3f353ec4bf80,0xbec4bf353f6d8000,0x3f6dbf35bec43f80,0x3ec43f35bf6d8000,0xbf6d3f353ec4bf80,0xbec4bf353f6d8000,0x3f6dbf35bec43f80,
0x3f1dbf783e2f3f55,0x3f393eacbf7f3ef1,0xbee63f80beb8bf35,0xbf58be163f77bf22,0x3f5fbf4ebe603f7b,0x3ecf3f2cbf733dc9,0xbf423f673cc9bf6d,0xbf13bf043f7ebe95,
0x3f4a3e79bf7c3f0e,0xbf313f71bd97bf62,0xbf65bd493f6fbf35,0x3f09bf7d3e893f46,0x3efc3f18bf7a3e48,0xbf6a3f3e3ea1bf7f,0xbf27bedb3f80bec4,0x3f51bf5cbdfb3f75,
0x3f04bf7f3eac3f35,0x3f3e3e95bf7d3f0e,0xbf4e3f623d49bf6d,0xbedbbf223f78be48,0xbe79bf463f670000,0x3f80bef1bf183f7b,0xbe163f75bf2cbec4,0xbf713dc93f5cbf55,
0x3f5c3dc9bf713f35,0xbf2c3f75be16bf55,0xbf18bef13f80bec4,0x3f67bf46be793f7b,0x3f78bf22bedb3f80,0x3d493f62bf4ebe48,0xbf7d3e953f3ebf6d,0x3eacbf7f3f043f0e,
0x3f39bf713dfb3f55,0x3ee63f18bf7c3e95,0xbe603f78bf27bec4,0xbf5fbd493f6abf46,0xbeb8bf2c3f77be48,0x3f7fbf04bf093f7f,0x3f513e16bf733f35,0xbf4a3f67bcc9bf62,
0x3f313eacbf7e3f0e,0xbf653f4e3e2fbf75,0xbf7a3e793f42bf6d,0x3efcbf803ecf3f22,0x3f6fbf3ebe893f7b,0x3d973f5cbf58bdc9,0xbf133f7dbea1bf35,0xbf1dbedb3f80bef1,
0xbf7f3f0e3ef1bf80,0x3e95bf7b3f223ec4,0x3f463e48bf753f35,0xbf623f553dc9bf6d,0xbdc9bf553f620000,0x3f75be48bf463f6d,0xbf223f7bbe95bf35,0xbef1bf0e3f7fbec4,
0xbdc9bf553f628000,0x3f75be48bf463f6d,0xbf223f7bbe95bf35,0xbef1bf0e3f7fbec4,0x3f7fbf0ebef13f80,0xbe953f7bbf22bec4,0xbf46be483f75bf35,0x3f62bf55bdc93f6d,
0xbf7c3eac3f27bf7b,0x3f1dbf7d3eb83f22,0x3f31bf783e893f35,0x3ea13f2cbf7a3e95,0x3f09bf803ee63f0e,0x3efc3f04bf803ef1,0x3ecf3f18bf7e3ec4,0xbf7f3edb3f13bf7f,
0x3e2fbf713f423e48,0x3f4a3e16bf6f3f46,0x3f393e79bf773f35,0xbf733f3e3e60bf75,0x3f583d49bf653f55,0xbf5f3f5c3cc9bf62,0xbf6a3f4e3dfbbf6d,0x3d97bf673f513dc9,
0xbf2cbe953f78bf35,0x3f7dbf22beac3f7b,0xbedb3f7fbf18bec4,0xbf04bef13f80bf0e,0xbd493f62bf5c0000,0xbf4ebdc93f67bf55,0x3f71bf46be163f6d,0xbe793f75bf3ebe48,
0x3f3ebf753e793f35,0x3e163f46bf713e48,0xbf673dc93f4ebf6d,0x3f5cbf623d493f55,0xbf803ef13f04bf80,0x3f18bf7f3edb3f0e,0x3eac3f22bf7d3ec4,0xbf783e953f2cbf7b,
0x3ea1bf783f393e48,0x3f093edbbf7e3f22,0x3f5fbd49bf513f6d,0xbf6f3f4e3d97bf62,0xbf273f7dbecfbf0e,0xbe2fbf3e3f77be95,0xbf1dbeac3f7abf35,0x3f80bf04bee63f7f,
0x3f73be79bf313f7b,0xbf583f67bdfbbf46,0xbefc3f80bf13bec4,0xbeb8bf183f7fbef1,0xbf42be163f6abf55,0x3f7cbf2cbe893f75,0x3f4abf713e603f35,0xbcc93f5cbf653dc9,
0x3f7bbec4bf0e3f80,0xbf553f6dbe48bf35,0x3e48bf6d3f550000,0x3f0e3ec4bf7b3f35,0xbf7b3ec43f0ebf80,0x3f55bf6d3e483f35,0xbe483f6dbf550000,0xbf0ebec43f7bbf35,
0xbe483f6dbf558000,0xbf0ebec43f7bbf35,0x3f7bbec4bf0e3f80,0xbf553f6dbe48bf35,0x3e48bf6d3f558000,0x3f0e3ec4bf7b3f35,0xbf7b3ec43f0ebf80,0x3f55bf6d3e483f35,
0x3ea13f18bf803f0e,0xbf583d493f4abf75,0xbf5f3f67be2fbf35,0x3eb8bf783f423dc9,0x3d97bf5c3f6abe48,0x3f133eacbf773f46,0x3f7ebf2cbe603f6d,0xbf313f7dbee6bef1,
0xbf733f4e3cc9bf55,0x3f09bf803f1d3e95,0xbefcbedb3f7cbf35,0x3f6fbe79bf273f7f,0x3f7fbf04becf3f7b,0xbf513f71be89bf22,0x3dfb3f3ebf7a3ec4,0xbf39be163f65bf62,
0xbf673f62be16bf35,0x3f04bf7f3f2c3e48,0x3d493f46bf783ec4,0xbf18be953f71bf55,0x3eacbf753f4e0000,0x3e793f22bf803f0e,0xbf3ebdc93f5cbf6d,0x3f7dbef1bedb3f7b,
0xbedbbef13f7dbf35,0x3f5cbdc9bf3e3f7b,0xbf803f223e79bf6d,0x3f4ebf753eac3f0e,0x3f71be95bf183f80,0xbf783f463d49bf55,0x3f2cbf7f3f043ec4,0xbe163f62bf673e48,
0xbe2fbf2c3f7fbf0e,0x3f1d3e79bf6a3f62,0x3f39bf7d3efc3ec4,0xbea13f71bf583dc9,0x3f7abedbbee63f7b,0xbf773f4ebcc9bf46,0x3eb83f04bf7e3f35,0xbf42bd493f51bf75,
0x3f7cbf3ebd973f55,0xbf4a3f78becfbef1,0x3f313e16bf5f3f6d,0xbf733eac3f09bf7f,0xbe603f67bf653e48,0xbe89bf183f80bf22,0xbf6f3f5cbdfbbf35,0x3f27bf803f133e95,
0xbf623e483f22bf80,0x3f7fbf0ebe953f6d,0xbf753f55bdc9bf35,0x3f46bf7b3ef13ec4,0xbef13f7bbf460000,0x3dc9bf553f75bec4,0x3e953f0ebf7f3f35,0xbf22be483f62bf6d,
0x3ef1bf7b3f468000,0xbdc93f55bf753ec4,0xbe95bf0e3f7fbf35,0x3f223e48bf623f6d,0xbf623e483f22bf80,0x3f7fbf0ebe953f6d,0xbf753f55bdc9bf35,0x3f46bf7b3ef13ec4,
0x3f31bf803f1d3e48,0xbee63f78bf513dc9,0x3f7abf4e3d973f35,0xbf5f3f71beb8bef1,0xbecfbedb3f77bf55,0x3f273e16bf583f75,0x3e2fbf5c3f73bec4,0x3dfb3f2cbf803f22,
0x3f393d49bf4a3f7b,0xbf653e793f13bf7f,0x3e603f18bf7f3f35,0xbefcbeac3f6fbf62,0x3f6abf673e893f0e,0xbf423f7dbf09be95,0x3f7cbf04bea13f6d,0xbf7e3f3e3cc9bf46,
0x3e163f22bf803f35,0xbeacbef13f78bf55,0x3f043e95bf673f6d,0xbf2cbdc93f4ebf7b,0xbf183f7fbf3e0000,0x3edbbf753f5cbe48,0xbe793f62bf713ec4,0x3d49bf463f7dbf0e,
0xbf7d3f46bd49bf35,0x3f71bf623e793f0e,0xbf5c3f75bedbbec4,0x3f3ebf7f3f183e48,0xbf4e3dc93f2cbf80,0x3f67be95bf043f7b,0xbf783ef13eacbf6d,0x3f80bf22be163f55,
0xbf1dbe163f51bf7b,0x3f313d49bf423f7f,0xbee6beac3f6abf6d,0x3f093e79bf5f3f75,0xbe89bf043f7abf55,0x3eb83edbbf733f62,0xbd97bf2c3f80bf35,0x3e2f3f18bf7e3f46,
0x3f4abf7d3f133e48,0xbf393f80bf27bdc9,0x3f65bf713ecf3ec4,0xbf583f78befcbe95,0x3f77bf5c3e603f0e,0xbf6f3f67bea1bef1,0x3f7fbf3e3cc93f35,0xbf7c3f4ebdfbbf22,
0xbf3500003f353f80,0x3f350000bf35bf80,0xbf3500003f353f80,0x3f350000bf35bf80,0xbf3500003f353f80,0x3f350000bf35bf80,0xbf3500003f353f80,0x3f350000bf35bf80,
0xbf35bf80bf358000,0x3f353f803f358000,0xbf35bf80bf358000,0x3f353f803f358000,0xbf35bf80bf358000,0x3f353f803f358000,0xbf35bf80bf358000,0x3f353f803f358000,
0x3e89be793e60be48,0x3eb8beac3ea1be95,0x3d97bd493cc90000,0x3e2fbe163dfbbdc9,0x3f1dbf183f13bf0e,0x3f31bf2c3f27bf22,0x3ee6bedb3ecfbec4,0x3f09bf043efcbef1,
0x3f77bf783f7abf7b,0x3f6fbf713f73bf75,0x3f7fbf803f80bf80,0x3f7cbf7d3f7ebf7f,0x3f4abf4e3f51bf55,0x3f39bf3e3f42bf46,0x3f65bf673f6abf6d,0x3f58bf5c3f5fbf62,
0x3f18bf223f2cbf35,0x3edbbef13f04bf0e,0x3e79be953eacbec4,0x3d49bdc93e16be48,0x3f7dbf7f3f80bf80,0x3f71bf753f78bf7b,0x3f5cbf623f67bf6d,0x3f3ebf463f4ebf55,
0xbf4e3f46bf3e3f35,0xbf673f62bf5c3f55,0xbf783f75bf713f6d,0xbf803f7fbf7d3f7b,0xbe163dc9bd498000,0xbeac3e95be793e48,0xbf043ef1bedb3ec4,0xbf2c3f22bf183f0e,
0xbf6a3f71bf773f7b,0xbf423f4ebf583f62,0xbf7c3f78bf733f6d,0xbf7e3f80bf803f7f,0xbf393f2cbf1d3f0e,0xbf653f5cbf513f46,0xbe603e16bd970000,0xbefc3edbbeb83e95,
0x3ecfbeac3e89be48,0x3f27bf183f09bef1,0xbe2f3e79bea13ec4,0x3dfbbd49bcc93dc9,0xbf313f3ebf4a3f55,0xbee63f04bf133f22,0xbf7a3f7dbf7f3f80,0xbf5f3f67bf6f3f75,
0xbf753f7bbf7f3f80,0xbf463f55bf623f6d,0xbef13f0ebf223f35,0xbdc93e48be953ec4,0x3e95be483dc90000,0x3f22bf0e3ef1bec4,0x3f62bf553f46bf35,0x3f7fbf7b3f75bf6d,
0x3e95be483dc98000,0x3f22bf0e3ef1bec4,0x3f62bf553f46bf35,0x3f7fbf7b3f75bf6d,0x3f75bf7b3f7fbf80,0x3f46bf553f62bf6d,0x3ef1bf0e3f22bf35,0x3dc9be483e95bec4,
0x3f7abf713f65bf55,0x3f77bf7d3f80bf7f,0x3eb8be793dfb0000,0x3f42bf2c3f13bef1,0xbe2f3d493d97be48,0xbf1d3f04becf3e95,0x3f39bf4e3f5fbf6d,0x3ea1bedb3f09bf22,
0x3e60beac3ee6bf0e,0xbe893e16bcc9bdc9,0x3f6fbf783f7ebf80,0x3f27bf3e3f51bf62,0xbf7c3f80bf7f3f7b,0xbf4a3f5cbf6a3f75,0xbf313f18befc3ec4,0xbf733f67bf583f46,
0xbf713f62bf4e3f35,0xbf783f7fbf803f7b,0xbf2c3f46bf5c3f6d,0xbe163e95bedb3f0e,0x3f67bf753f7dbf80,0x3f04bf223f3ebf55,0xbd49bdc93e79bec4,0xbf183ef1beac3e48,
0xbeac3ef1bf183f35,0x3e79bdc9bd493e48,0x3f3ebf223f04bec4,0x3f7dbf753f67bf55,0xbedb3e95be168000,0xbf5c3f46bf2c3f0e,0xbf803f7fbf783f6d,0xbf4e3f62bf713f7b,
0x3f7fbf783f6abf55,0x3f51bf673f77bf7f,0x3dfb3d49be603ec4,0x3f39bf183ee6be95,0xbf733f7dbf803f7b,0xbf093f2cbf4a3f62,0xbefc3eacbe2f0000,0xbf6f3f5cbf423f22,
0x3d97be793ecfbf0e,0xbf133edbbe893dc9,0x3f7ebf803f7abf6d,0x3f31bf4e3f65bf75,0x3ea1be16bcc93e48,0x3f58bf3e3f1dbef1,0xbf5f3f71bf7c3f80,0xbeb83f04bf273f46,
0xbf553f6dbf7b3f80,0xbe483ec4bf0e3f35,0x3f0ebec43e480000,0x3f7bbf6d3f55bf35,0x3f55bf6d3f7bbf80,0x3e48bec43f0ebf35,0xbf0e3ec4be480000,0xbf7b3f6dbf553f35,
0x3f0ebec43e488000,0x3f7bbf6d3f55bf35,0x3f55bf6d3f7bbf80,0x3e48bec43f0ebf35,0xbf0e3ec4be488000,0xbf7b3f6dbf553f35,0xbf553f6dbf7b3f80,0xbe483ec4bf0e3f35,
0x3f27bf4e3f6abf7b,0xbe2fbd493e89bef1,0x3f1dbedb3e600000,0x3f80bf783f65bf46,0xbea13f04bf313f55,0x3f09beac3dfb3dc9,0xbf5f3f3ebf133ec4,0xbf6f3f7dbf7f3f75,
0xbf423f18becf3e48,0xbf7c3f80bf773f62,0x3f4abf673f7abf80,0x3cc9be793ee6bf22,0x3f73bf5c3f39bf0e,0x3f58bf713f7ebf7f,0xbefc3f2cbf513f6d,0x3eb8be16bd973e95,
0xbd493e95bf043f35,0x3f4ebf223edbbe48,0x3f71bf7f3f7dbf6d,0x3e79bef13f2cbf55,0x3f3ebf623f78bf80,0xbe16bdc93eacbf0e,0xbf673f46bf183ec4,0xbf5c3f75bf803f7b,
0x3f80bf753f5cbf35,0x3f18bf463f67bf7b,0xbeac3dc93e16bec4,0xbf783f62bf3e3f0e,0xbf2c3ef1be798000,0xbf7d3f7fbf713f55,0xbedb3f22bf4e3f6d,0x3f04be953d493e48,
0xbf583f2cbee63e48,0xbf5f3f78bf803f75,0x3f6abf7d3f7ebf6d,0x3d97beac3f13bf46,0xbe2f3edbbf273f55,0x3f4abf183eb8bdc9,0xbf393f04be890000,0xbf733f80bf7a3f62,
0xbf093f3ebf653f7b,0x3efcbe79bcc93e95,0xbecf3e163dfbbec4,0xbf7f3f71bf513f22,0x3f7cbf673f42bf0e,0x3f1dbf4e3f6fbf7f,0xbf313f5cbf773f80,0x3ea1bd49be603ef1,
0xbf223f55bf753f80,0x3ef1be48bdc93ec4,0x3f7fbf7b3f62bf35,0x3e95bf0e3f46bf6d,0xbf463f0ebe950000,0xbf623f7bbf7f3f6d,0x3dc93e48bef13f35,0x3f75bf553f22bec4,
0x3f46bf0e3e958000,0x3f62bf7b3f7fbf6d,0xbdc9be483ef1bf35,0xbf753f55bf223ec4,0xbf223f55bf753f80,0x3ef1be48bdc93ec4,0x3f7fbf7b3f62bf35,0x3e95bf0e3f46bf6d,
0xbeb83d493e89bf0e,0xbf7f3f78bf583f22,0x3f51bf183ea10000,0x3f4abf713f80bf75,0x3f39bf673f7ebf7b,0xbee63e163e2fbef1,0xbe603f04bf423f6d,0x3f5fbf2c3ecfbdc9,
0xbf6f3f80bf773f55,0x3d973e79bf093f46,0x3f13bf4e3f73bf80,0xbf1d3eacbcc9be95,0xbf313edbbdfbbe48,0xbf653f7dbf7c3f62,0x3f7abf5c3f27bec4,0x3efcbf3e3f6abf7f,
0x3f78bf7f3f67bf35,0xbd49be953f18bf55,0xbf7d3f62bf2c3ec4,0xbeac3f22bf5c3f7b,0x3f04bf463f71bf80,0xbf3e3ef1be16be48,0xbf4e3f75bf803f6d,0x3edbbdc9be793f0e,
0xbe79bdc93edbbf35,0xbf803f75bf4e3f0e,0xbe163ef1bf3e3f6d,0x3f71bf463f04be48,0xbf5c3f22beac8000,0xbf2c3f62bf7d3f7b,0x3f18be95bd493ec4,0x3f67bf7f3f78bf55,
0x3efcbe16be603f0e,0x3f6abf803f73bf46,0xbf273eac3cc9bec4,0xbf513f78bf7e3f62,0x3f4abf043e2f3e48,0x3f31bf673f7fbf75,0xbf653f2cbeb80000,0xbf093f4ebf773f7f,
0x3f5fbf7d3f7abf55,0xbecf3d493ea1bf22,0xbf423f71bf803f6d,0x3f13be79bdfb3ef1,0x3f1dbf5c3f7cbf7b,0xbf393edbbd97be95,0xbee63f3ebf6f3f80,0x3f58bf183e893dc9,
0xbec43f35bf6d3f80,0x3f6dbf353ec40000,0x3ec4bf353f6dbf80,0xbf6d3f35bec40000,0xbec43f35bf6d3f80,0x3f6dbf353ec40000,0x3ec4bf353f6dbf80,0xbf6d3f35bec40000,
0x3f6dbf353ec48000,0x3ec4bf353f6dbf80,0xbf6d3f35bec48000,0xbec43f35bf6d3f80,0x3f6dbf353ec48000,0x3ec4bf353f6dbf80,0xbf6d3f35bec48000,0xbec43f35bf6d3f80,
0xbf7e3f5cbf133e48,0xbcc93edbbf423f75,0x3f73bf3e3ecf0000,0x3e60bf183f5fbf7f,0xbf773f7dbf583f0e,0x3eb83d49bee63f46,0x3f7fbf713f39bec4,0xbe2fbe793f1dbf62,
0xbdfb3f04bf513f7b,0x3f80bf673f27be95,0x3ea1bf2c3f6abf80,0xbf7a3f4ebefc3dc9,0x3e893e16bf093f55,0x3f6fbf803f65bf22,0xbd97beac3f31bf6d,0xbf7c3f78bf4a3ef1,
0xbf043dc93eacbf35,0xbf3e3f75bf7d3f55,0x3f4ebef13d493ec4,0x3edbbf463f78bf7b,0x3e79bf223f67bf80,0xbf803f62bf183e48,0x3e163e95bf2c3f6d,0x3f71bf7f3f5cbf0e,
0xbf5c3f7fbf713f35,0x3f2cbe95be163f0e,0x3f18bf623f80bf6d,0xbf673f22be79be48,0xbf783f46bedb8000,0xbd493ef1bf4e3f7b,0x3f7dbf753f3ebec4,0xbeacbdc93f04bf55,
0xbcc9bedb3f4abf7b,0xbf733f7dbf513ef1,0xbf093f5cbf7f3f6d,0x3f77bf3e3eb83dc9,0x3f6abf803f5fbf0e,0xbf273e793e60bf22,0xbf7c3f4ebee60000,0x3dfb3eacbf393f75,
0xbf803f67bf1d3e48,0x3ea13e16bf133f62,0x3f58bf043d973ec4,0x3e89bf2c3f6fbf7f,0xbecfbd493efcbf55,0xbf423f78bf7a3f46,0xbe2f3f18bf653f80,0x3f7ebf713f31be95,
0xbdc93f0ebf623f80,0x3f75bf7b3f46bec4,0xbf223e483e95bf35,0xbef13f55bf7f3f6d,0x3f7fbf553ef10000,0xbe95be483f22bf6d,0xbf463f7bbf753f35,0x3f62bf0e3dc93ec4,
0x3f7fbf553ef18000,0xbe95be483f22bf6d,0xbf463f7bbf753f35,0x3f62bf0e3dc93ec4,0x3dc9bf0e3f62bf80,0xbf753f7bbf463ec4,0x3f22be48be953f35,0x3ef1bf553f7fbf6d,
0xbf133f67bf7f3f55,0x3f7ebf4e3ecf3dc9,0x3f80bf5c3efc0000,0xbee6bd493f09bf62,0x3f7abf3e3ea13e48,0xbe89be793f31bf75,0xbeb8be163f1dbf6d,0xbf273f71bf7c3f46,
0x3f51bedbbd973f0e,0x3dfbbf183f6abf7f,0x3cc9bf043f5fbf80,0xbf653f80bf583ef1,0x3e60bf2c3f73bf7b,0xbf773f78bf393e95,0xbf6f3f7dbf4a3ec4,0x3f42beacbe2f3f22,
0xbf2c3f75bf783f35,0x3f7dbf463eac3e48,0xbedbbdc93f18bf6d,0xbf043f62bf803f55,0xbd49bef13f5cbf80,0xbf4e3f7fbf673f0e,0x3f71bf223e163ec4,0xbe79be953f3ebf7b,
0x3f3ebe95be793f35,0x3e16bf223f71bf7b,0xbf673f7fbf4e3ec4,0x3f5cbef1bd493f0e,0xbf803f62bf048000,0x3f18bdc9bedb3f55,0x3eacbf463f7dbf6d,0xbf783f75bf2c3e48,
0xbee63f5cbf803f55,0x3f7abf713f1dbdc9,0x3f77bf2c3e2f3ec4,0xbecfbe163f27bf75,0x3d97bf183f6fbf7b,0xbf513f80bf5f3ef1,0xbf7e3f67bf090000,0x3f39be79bea13f46,
0x3f65bf04bcc93f0e,0xbe60beac3f4abf7f,0x3e89bf3e3f7cbf6d,0xbf6a3f7dbf423e95,0xbf7f3f4ebeb8be48,0x3f13bd49befc3f62,0x3dfb3edbbf583f80,0x3f31bf783f73bf22,
0x3e483ec4bf553f80,0x3f0ebf6d3f7bbf35,0xbf7b3f6dbf0e0000,0x3f55bec4be483f35,0xbe48bec43f55bf80,0xbf0e3f6dbf7b3f35,0x3f7bbf6d3f0e0000,0xbf553ec43e48bf35,
0x3f7bbf6d3f0e8000,0xbf553ec43e48bf35,0x3e483ec4bf553f80,0x3f0ebf6d3f7bbf35,0xbf7b3f6dbf0e8000,0x3f55bec4be483f35,0xbe48bec43f55bf80,0xbf0e3f6dbf7b3f35,
0x3ee63e16bf313f7b,0x3e60bf3e3f7ebf62,0x3f77bf713f130000,0xbf6a3f043d97bf22,0xbf423e793eb8bf55,0x3e2f3edbbf5f3f7f,0xbf4a3f80bf583ec4,0x3f80bf4e3ea13e95,
0x3f65bf7d3f39be48,0xbf7a3f2cbdfbbef1,0xbe89beac3f51bf80,0xbecf3f5cbf7f3f46,0xbf273f78bf6f3f0e,0x3f7cbf673efc3dc9,0x3f1dbd49bf093f6d,0x3cc9bf183f73bf75,
0x3f67bef1be163f35,0xbf04bdc93f2cbf7b,0xbd493f22bf783f6d,0x3f18bf753f71bf0e,0xbeacbe953f4ebf80,0xbe793f46bf803f55,0x3f3ebf7f3f5cbec4,0xbf7d3f62bedbbe48,
0x3edbbf623f7dbf35,0xbf5c3f7fbf3e3e48,0x3f80bf463e793ec4,0xbf4e3e953eacbf55,0xbf713f75bf188000,0x3f78bf223d493f0e,0xbf2c3dc93f04bf6d,0x3e163ef1bf673f7b,
0x3f51bf803f42be48,0xbf7e3f5cbeb8be95,0xbcc9bf183f77bf6d,0xbee63f67bf7a3f22,0xbf583eac3ea1bf55,0x3efc3e16bf393f7f,0xbf6a3f78bf1d0000,0x3f7fbf3e3e2f3ef1,
0xbf13bd493f27bf7b,0x3dfb3f04bf6f3f75,0xbf803f4ebe89bec4,0x3f65bedbbe603f46,0xbf093f71bf733f0e,0x3f5fbf7d3f31bdc9,0x3ecf3e79bf4a3f80,0x3d97bf2c3f7cbf62,
0x3ef13e48bf463f80,0xbdc9bf0e3f75bf6d,0xbe953f55bf7f3f35,0x3f22bf7b3f62bec4,0xbf623f7bbf220000,0x3f7fbf553e953ec4,0xbf753f0e3dc9bf35,0x3f46be48bef13f6d,
0x3f62bf7b3f228000,0xbf7f3f55be95bec4,0x3f75bf0ebdc93f35,0xbf463e483ef1bf6d,0x3ef13e48bf463f80,0xbdc9bf0e3f75bf6d,0xbe953f55bf7f3f35,0x3f22bf7b3f62bec4,
0x3f80bf3e3dfb3f0e,0xbf733f043e2fbf46,0x3f58bf7d3f270000,0xbf773f67becfbe95,0x3eb83eacbf5f3f7b,0xbd97bf183f7abf62,0x3f51be79bee63f6d,0xbf1dbd493f31bf7f,
0x3cc9bf2c3f7ebf55,0xbea13f5cbf7c3f22,0xbf09be163f42bf80,0x3e893edbbf6a3f75,0x3f6fbf713efc3e48,0xbf7f3f4ebe60bef1,0x3f13bf783f65bec4,0xbf4a3f80bf393dc9,
0x3e16bf463f80bf35,0xbeac3f62bf783f0e,0x3f04bf753f67bec4,0xbf2c3f7fbf4e3e48,0xbf18bdc93f3ebf80,0x3edb3e95bf5c3f7b,0xbe79bef13f71bf6d,0x3d493f22bf7d3f55,
0xbf7d3f223d49bf35,0x3f71bef1be793f55,0xbf5c3e953edbbf6d,0x3f3ebdc9bf183f7b,0xbf4e3f7fbf2c8000,0x3f67bf753f043e48,0xbf783f62beacbec4,0x3f80bf463e163f0e,
0xbf7e3f4ebe2fbf0e,0x3f80bf3e3d973f22,0xbf733f67beb8bec4,0x3f7abf5c3e893ef1,0xbf5f3f78bf09be48,0x3f6abf713ee63e95,0xbf423f80bf310000,0x3f51bf7d3f1d3dc9,
0x3dfb3f18bf7c3f55,0xbcc9bf2c3f7fbf46,0x3ea13edbbf6f3f6d,0xbe60bf043f77bf62,0x3efc3e79bf583f7b,0xbecfbeac3f65bf75,0x3f273d49bf393f80,0xbf13be163f4abf7f,
0xbf3500003f353f80,0x3f350000bf35bf80,0xbf3500003f353f80,0x3f350000bf35bf80,0xbf3500003f353f80,0x3f350000bf35bf80,0xbf3500003f353f80,0x3f350000bf35bf80,
0xbf35bf80bf358000,0x3f353f803f358000,0xbf35bf80bf358000,0x3f353f803f358000,0xbf35bf80bf358000,0x3f353f803f358000,0xbf35bf80bf358000,0x3f353f803f358000,
0x3f5fbf5c3f58bf55,0x3f6abf673f65bf62,0x3f42bf3e3f39bf35,0x3f51bf4e3f4abf46,0x3f7ebf7d3f7cbf7b,0x3f80bf803f7fbf7f,0x3f73bf713f6fbf6d,0x3f7abf783f77bf75,
0x3efcbf043f09bf0e,0x3ecfbedb3ee6bef1,0x3f27bf2c3f31bf35,0x3f13bf183f1dbf22,0x3dfbbe163e2fbe48,0x3cc9bd493d97bdc9,0x3ea1beac3eb8bec4,0x3e60be793e89be95,
0xbf4e3f46bf3e3f35,0xbf673f62bf5c3f55,0xbf783f75bf713f6d,0xbf803f7fbf7d3f7b,0xbe163dc9bd490000,0xbeac3e95be793e48,0xbf043ef1bedb3ec4,0xbf2c3f22bf183f0e,
0xbf183f22bf2c3f35,0xbedb3ef1bf043f0e,0xbe793e95beac3ec4,0xbd493dc9be163e48,0xbf7d3f7fbf803f80,0xbf713f75bf783f7b,0xbf5c3f62bf673f6d,0xbf3e3f46bf4e3f55,
0x3f6fbf673f5fbf55,0x3f7fbf7d3f7abf75,0x3f13bf043ee6bec4,0x3f4abf3e3f31bf22,0x3cc93d49bdfb3e48,0x3ea1be793e2fbdc9,0xbf093f18bf273f35,0xbe893eacbecf3ef1,
0x3eb8bedb3efcbf0e,0x3d97be163e60be95,0x3f51bf5c3f65bf6d,0x3f1dbf2c3f39bf46,0x3f80bf803f7ebf7b,0x3f73bf783f7cbf7f,0x3f58bf4e3f42bf35,0x3f77bf713f6abf62,
0x3f75bf7b3f7fbf80,0x3f46bf553f62bf6d,0x3ef1bf0e3f22bf35,0x3dc9be483e95bec4,0xbe953e48bdc90000,0xbf223f0ebef13ec4,0xbf623f55bf463f35,0xbf7f3f7bbf753f6d,
0xbe953e48bdc98000,0xbf223f0ebef13ec4,0xbf623f55bf463f35,0xbf7f3f7bbf753f6d,0xbf753f7bbf7f3f80,0xbf463f55bf623f6d,0xbef13f0ebf223f35,0xbdc93e48be953ec4,
0xbf583f67bf733f7b,0xbefc3f18bf313f46,0xbf6a3f5cbf4a3f35,0xbf7f3f80bf7c3f75,0x3f51bf3e3f27bf0e,0x3f7ebf783f6fbf62,0xbcc93e16be893ec4,0x3ee6beac3e60bdc9,
0x3f09bedb3ea1be48,0x3f5fbf4e3f39bf22,0xbecf3f04bf1d3f35,0x3d973d49be2f3e95,0x3f13bf2c3f42bf55,0x3dfbbe793eb8bef1,0x3f80bf7d3f77bf6d,0x3f65bf713f7abf7f,
0x3eacbef13f18bf35,0xbe793dc93d49be48,0xbf3e3f22bf043ec4,0xbf7d3f75bf673f55,0x3edbbe953e160000,0x3f5cbf463f2cbf0e,0x3f80bf7f3f78bf6d,0x3f4ebf623f71bf7b,
0xbf713f62bf4e3f35,0xbf783f7fbf803f7b,0xbf2c3f46bf5c3f6d,0xbe163e95bedb3f0e,0x3f67bf753f7dbf80,0x3f04bf223f3ebf55,0xbd49bdc93e79bec4,0xbf183ef1beac3e48,
0x3f27bf043eb8be48,0x3f7cbf713f5fbf46,0xbf1d3f3ebf583f6d,0x3cc93e16bea13ef1,0xbf653f4ebf313f0e,0xbf7a3f80bf7e3f75,0x3e89bedb3f13bf35,0xbecf3e79bd97bdc9,
0x3f42bf5c3f6fbf7b,0x3e2fbeac3efcbf22,0x3f4abf2c3f09bec4,0x3f80bf7d3f73bf62,0xbee63f18bf393f55,0x3e60bd49bdfb3e95,0xbf773f67bf513f35,0xbf6a3f78bf7f3f7f,
0xbf553f6dbf7b3f80,0xbe483ec4bf0e3f35,0x3f0ebec43e480000,0x3f7bbf6d3f55bf35,0x3f55bf6d3f7bbf80,0x3e48bec43f0ebf35,0xbf0e3ec4be480000,0xbf7b3f6dbf553f35,
0x3f0ebec43e488000,0x3f7bbf6d3f55bf35,0x3f55bf6d3f7bbf80,0x3e48bec43f0ebf35,0xbf0e3ec4be488000,0xbf7b3f6dbf553f35,0xbf553f6dbf7b3f80,0xbe483ec4bf0e3f35,
0xbd97be163eb8bf0e,0xbf513f2cbefc3e95,0x3f7ebf713f58bf35,0x3f39bf5c3f73bf7f,0x3ee6be793cc93e48,0x3f7abf673f4abf22,0xbf773f80bf7c3f6d,0xbecf3f18bf423f62,
0xbf7f3f7dbf6f3f55,0xbf133f3ebf5f3f75,0x3dfbbeac3f09bf35,0xbf313f04bea13dc9,0x3f65bf783f80bf7b,0x3e60bedb3f1dbf46,0x3e89bd49be2f3ec4,0x3f6abf4e3f27bef1,
0x3f80bf753f5cbf35,0x3f18bf463f67bf7b,0xbeac3dc93e16bec4,0xbf783f62bf3e3f0e,0xbf2c3ef1be790000,0xbf7d3f7fbf713f55,0xbedb3f22bf4e3f6d,0x3f04be953d493e48,
0x3d49be953f04bf35,0xbf4e3f22bedb3e48,0xbf713f7fbf7d3f6d,0xbe793ef1bf2c3f55,0xbf3e3f62bf783f80,0x3e163dc9beac3f0e,0x3f67bf463f18bec4,0x3f5cbf753f80bf7b,
0x3e603d49bea13f0e,0x3f77bf5c3f31bef1,0xbf6f3f4ebf1d3ec4,0xbf423f67bf7c3f7f,0x3f51bf713f7fbf7b,0xbdfbbe163ecfbf22,0x3cc93e79befc3f35,0x3f65bf3e3f09be95,
0x3f7abf803f73bf55,0x3e89bf043f39bf62,0xbeb83f18bf4a3f6d,0x3f27bedb3e2f3dc9,0xbf133eacbd97be48,0xbf7e3f7dbf6a3f46,0x3f80bf783f5fbf35,0x3ee6bf2c3f58bf75,
0x3f22bf553f75bf80,0xbef13e483dc9bec4,0xbf7f3f7bbf623f35,0xbe953f0ebf463f6d,0x3f46bf0e3e950000,0x3f62bf7b3f7fbf6d,0xbdc9be483ef1bf35,0xbf753f55bf223ec4,
0xbf463f0ebe958000,0xbf623f7bbf7f3f6d,0x3dc93e48bef13f35,0x3f75bf553f22bec4,0x3f22bf553f75bf80,0xbef13e483dc9bec4,0xbf7f3f7bbf623f35,0xbe953f0ebf463f6d,
0x3f6abf3e3efcbe48,0x3f27bf5c3f7abf7f,0xbf7c3f7dbf653f35,0xbdfb3edbbf313f62,0xbcc93eacbf1d3f55,0x3f73bf4e3f13be95,0xbf093e793d97bec4,0xbf773f80bf6f3f46,
0x3ecfbf2c3f5fbf7b,0xbf423f04be60bdc9,0x3e2f3e16bee63f35,0x3f7ebf673f39bef1,0x3f80bf713f4abf0e,0x3ea1bf183f51bf75,0xbf583f78bf7f3f6d,0x3e893d49beb83f22,
0x3e793dc9bedb3f35,0x3f80bf753f4ebf0e,0x3e16bef13f3ebf6d,0xbf713f46bf043e48,0x3f5cbf223eac0000,0x3f2cbf623f7dbf7b,0xbf183e953d49bec4,0xbf673f7fbf783f55,
0x3f78bf7f3f67bf35,0xbd49be953f18bf55,0xbf7d3f62bf2c3ec4,0xbeac3f22bf5c3f7b,0x3f04bf463f71bf80,0xbf3e3ef1be16be48,0xbf4e3f75bf803f6d,0x3edbbdc9be793f0e,
0xbe893f18bf583f7b,0x3f6fbf3e3ee6bdc9,0x3d97bedb3f39bf6d,0xbf7c3f5cbf1d3e95,0x3dfb3e79bf133f55,0x3f80bf713f42bef1,0xbea1bd493ecfbf35,0xbf7a3f7dbf5f3f22,
0x3f77bf4e3f09be48,0x3eb8bf2c3f65bf7f,0xbf7f3f67bf313ec4,0xbe2f3f04bf4a3f75,0x3f7ebf783f51bf0e,0xbcc9beac3f27bf62,0xbf733f80bf6a3f35,0x3e603e16befc3f46,
0xbec43f35bf6d3f80,0x3f6dbf353ec40000,0x3ec4bf353f6dbf80,0xbf6d3f35bec40000,0xbec43f35bf6d3f80,0x3f6dbf353ec40000,0x3ec4bf353f6dbf80,0xbf6d3f35bec40000,
0x3f6dbf353ec48000,0x3ec4bf353f6dbf80,0xbf6d3f35bec48000,0xbec43f35bf6d3f80,0x3f6dbf353ec48000,0x3ec4bf353f6dbf80,0xbf6d3f35bec48000,0xbec43f35bf6d3f80,
0xbf4a3f78bf7c3f55,0x3f31beacbd973ef1,0x3f65bf803f6fbf35,0xbf093e163e89bf22,0xbefc3f4ebf7a3f7b,0x3f6abf2c3ea13dc9,0x3f27bf673f80bf6d,0xbf513f04bdfbbe95,
0x3f1dbe79be2f3f0e,0x3f39bf713f7fbf62,0xbee63d493eb8bf35,0xbf583f7dbf773f46,0x3f5fbf183e603e48,0x3ecfbf3e3f73bf7f,0xbf423edbbcc9bec4,0xbf133f5cbf7e3f75,
0xbf5c3f7fbf713f35,0x3f2cbe95be163f0e,0x3f18bf623f80bf6d,0xbf673f22be79be48,0xbf783f46bedb0000,0xbd493ef1bf4e3f7b,0x3f7dbf753f3ebec4,0xbeacbdc93f04bf55,
0x3f04bdc9beac3f35,0x3f3ebf753f7dbf55,0xbf4e3ef1bd49bec4,0xbedb3f46bf783f7b,0xbe793f22bf673f80,0x3f80bf623f18be48,0xbe16be953f2cbf6d,0xbf713f7fbf5c3f0e,
0xbf313f71bf7e3f55,0x3f65bf183e2f3e95,0x3f7abf783f42bec4,0xbefc3d493ecfbf46,0xbf6f3f2cbe89be48,0xbd973f04bf583f7f,0x3f13be16bea13f35,0x3f1dbf673f80bf62,
0x3f39beacbdfb3f0e,0x3ee6bf4e3f7cbf75,0xbe60be793f27bf6d,0xbf5f3f80bf6a3f22,0xbeb83f3ebf773f7b,0x3f7fbf5c3f09bdc9,0x3f51bf7d3f73bf35,0xbf4a3edb3cc9bef1,
0x3dc9bf0e3f62bf80,0xbf753f7bbf463ec4,0x3f22be48be953f35,0x3ef1bf553f7fbf6d,0xbf7f3f55bef10000,0x3e953e48bf223f6d,0x3f46bf7b3f75bf35,0xbf623f0ebdc9bec4,
0xbf7f3f55bef18000,0x3e953e48bf223f6d,0x3f46bf7b3f75bf35,0xbf623f0ebdc9bec4,0xbdc93f0ebf623f80,0x3f75bf7b3f46bec4,0xbf223e483e95bf35,0xbef13f55bf7f3f6d,
0xbe2fbeac3f42bf7b,0xbf4a3f7dbf6f3f22,0xbf393f78bf773f35,0x3f73bf2c3e603e95,0xbf583f80bf653f0e,0x3f5fbf043cc93ef1,0x3f6abf183dfb3ec4,0xbd97bedb3f51bf7f,
0xbf7c3f71bf273e48,0x3f1dbe16beb83f46,0x3f31be79be893f35,0x3ea1bf3e3f7abf75,0x3f09bd49bee63f55,0x3efcbf5c3f80bf62,0x3ecfbf4e3f7ebf6d,0xbf7f3f67bf133dc9,
0xbf3e3e953e79bf35,0xbe163f22bf713f7b,0x3f67bf7f3f4ebec4,0xbf5c3ef13d49bf0e,0x3f80bf623f040000,0xbf183dc93edbbf55,0xbeac3f46bf7d3f6d,0x3f78bf753f2cbe48,
0xbf2c3f75bf783f35,0x3f7dbf463eac3e48,0xbedbbdc93f18bf6d,0xbf043f62bf803f55,0xbd49bef13f5cbf80,0xbf4e3f7fbf673f0e,0x3f71bf223e163ec4,0xbe79be953f3ebf7b,
0xbf733f78bf313e48,0x3f58bedbbdfb3f22,0x3efc3d49bf133f6d,0x3eb8bf4e3f7fbf62,0x3f42bf7d3f6abf0e,0xbf7c3f3ebe89be95,0xbf4a3eac3e60bf35,0x3cc93f04bf653f7f,
0x3ea13e79bf393f7b,0x3f09bf673f7ebf46,0x3f5fbf803f51bec4,0xbf6f3f18bd97bef1,0xbf273e163ecfbf55,0xbe2f3f2cbf773f75,0xbf1d3f71bf7a3f35,0x3f80bf5c3ee63dc9,
0x3e483ec4bf553f80,0x3f0ebf6d3f7bbf35,0xbf7b3f6dbf0e0000,0x3f55bec4be483f35,0xbe48bec43f55bf80,0xbf0e3f6dbf7b3f35,0x3f7bbf6d3f0e0000,0xbf553ec43e48bf35,
0x3f7bbf6d3f0e8000,0xbf553ec43e48bf35,0x3e483ec4bf553f80,0x3f0ebf6d3f7bbf35,0xbf7b3f6dbf0e8000,0x3f55bec4be483f35,0xbe48bec43f55bf80,0xbf0e3f6dbf7b3f35,
0x3f73bf183cc93f0e,0xbf09bd493f1dbf75,0x3efcbf673f7cbf35,0xbf6f3f78bf273dc9,0xbf7f3f5cbecfbe48,0x3f51beacbe893f46,0xbdfb3f2cbf7a3f6d,0x3f39bf7d3f65bef1,
0x3ea1bf4e3f80bf55,0xbf583f80bf4a3e95,0xbf5f3edb3e2fbf35,0x3eb83e79bf423f7f,0x3d973f04bf6a3f7b,0x3f13bf713f77bf22,0x3f7ebf3e3e603ec4,0xbf313e163ee6bf62,
0x3edbbf623f7dbf35,0xbf5c3f7fbf3e3e48,0x3f80bf463e793ec4,0xbf4e3e953eacbf55,0xbf713f75bf180000,0x3f78bf223d493f0e,0xbf2c3dc93f04bf6d,0x3e163ef1bf673f7b,
0xbf673ef13e16bf35,0x3f043dc9bf2c3f7b,0x3d49bf223f78bf6d,0xbf183f75bf713f0e,0x3eac3e95bf4e3f80,0x3e79bf463f80bf55,0xbf3e3f7fbf5c3ec4,0x3f7dbf623edb3e48,
0xbf7c3f2cbd97bf0e,0x3f4abe79becf3f62,0xbf313f7dbf5f3ec4,0x3f73bf713f093dc9,0x3e603edbbf653f7b,0x3e89bf4e3f80bf46,0x3f6fbf04bdfb3f35,0xbf273d493f13bf75,
0xbe2f3f3ebf7f3f55,0x3f1dbf783f6abef1,0x3f39be16befc3f6d,0xbea1beac3f58bf7f,0x3f7abf673ee63e48,0xbf773f183cc9bf22,0x3eb8bf5c3f7ebf35,0xbf423f80bf513e95,
0xbef1be483f46bf80,0x3dc93f0ebf753f6d,0x3e95bf553f7fbf35,0xbf223f7bbf623ec4,0x3f62bf7b3f220000,0xbf7f3f55be95bec4,0x3f75bf0ebdc93f35,0xbf463e483ef1bf6d,
0xbf623f7bbf228000,0x3f7fbf553e953ec4,0xbf753f0e3dc9bf35,0x3f46be48bef13f6d,0xbef1be483f46bf80,0x3dc93f0ebf753f6d,0x3e95bf553f7fbf35,0xbf223f7bbf623ec4,
0xbf393f80bf4a3e48,0x3f65bf783f133dc9,0xbe603f4ebf7f3f35,0x3efcbf713f6fbef1,0xbf6a3edb3e89bf55,0x3f42be16bf093f75,0xbf7c3f5cbea1bec4,0x3f7ebf2c3cc93f22,
0x3f31bd49bf1d3f7b,0xbee6be793f51bf7f,0x3f7abf18bd973f35,0xbf5f3eac3eb8bf62,0xbecf3f67bf773f0e,0x3f27bf7d3f58be95,0x3e2f3f04bf733f6d,0x3dfbbf3e3f80bf46,
0x3f7dbf22bd493f35,0xbf713ef13e79bf55,0x3f5cbe95bedb3f6d,0xbf3e3dc93f18bf7b,0x3f4ebf7f3f2c0000,0xbf673f75bf04be48,0x3f78bf623eac3ec4,0xbf803f46be16bf0e,
0x3e16bf463f80bf35,0xbeac3f62bf783f0e,0x3f04bf753f67bec4,0xbf2c3f7fbf4e3e48,0xbf18bdc93f3ebf80,0x3edb3e95bf5c3f7b,0xbe79bef13f71bf6d,0x3d493f22bf7d3f55,
0xbf4a3e163f13bf7b,0x3f39bd49bf273f7f,0xbf653eac3ecfbf6d,0x3f58be79befc3f75,0xbf773f043e60bf55,0x3f6fbedbbea13f62,0xbf7f3f2c3cc9bf35,0x3f7cbf18bdfb3f46,
0xbf1d3f7dbf513e48,0x3f31bf803f42bdc9,0xbee63f71bf6a3ec4,0x3f09bf783f5fbe95,0xbe893f5cbf7a3f0e,0x3eb8bf673f73bef1,0xbd973f3ebf803f35,0x3e2fbf4e3f7ebf22,
0x3f350000bf353f80,0xbf3500003f35bf80,0x3f350000bf353f80,0xbf3500003f35bf80,0x3f350000bf353f80,0xbf3500003f35bf80,0x3f350000bf353f80,0xbf3500003f35bf80,
0xbf353f80bf358000,0x3f35bf803f358000,0xbf353f80bf358000,0x3f35bf803f358000,0xbf353f80bf358000,0x3f35bf803f358000,0xbf353f80bf358000,0x3f35bf803f358000,
0xbf773e793f7abe48,0xbf6f3eac3f73be95,0xbf7f3d493f800000,0xbf7c3e163f7ebdc9,0xbf4a3f183f51bf0e,0xbf393f2c3f42bf22,0xbf653edb3f6abec4,0xbf583f043f5fbef1,
0x3e893f78be60bf7b,0x3eb83f71bea1bf75,0x3d973f80bcc9bf80,0x3e2f3f7dbdfbbf7f,0x3f1d3f4ebf13bf55,0x3f313f3ebf27bf46,0x3ee63f67becfbf6d,0x3f093f5cbefcbf62,
0x3f4e3f22bf3ebf35,0x3f673ef1bf5cbf0e,0x3f783e95bf71bec4,0x3f803dc9bf7dbe48,0x3e163f7fbd49bf80,0x3eac3f75be79bf7b,0x3f043f62bedbbf6d,0x3f2c3f46bf18bf55,
0x3f18bf46bf2c3f35,0x3edbbf62bf043f55,0x3e79bf75beac3f6d,0x3d49bf7fbe163f7b,0x3f7dbdc9bf808000,0x3f71be95bf783e48,0x3f5cbef1bf673ec4,0x3f3ebf22bf4e3f0e,
0xbecfbf713e893f7b,0xbf27bf4e3f093f62,0x3e2fbf78bea13f6d,0xbdfbbf80bcc93f7f,0x3f31bf2cbf4a3f0e,0x3ee6bf5cbf133f46,0x3f7abe16bf7f0000,0x3f5fbedbbf6f3e95,
0xbf6a3eac3f77be48,0xbf423f183f58bef1,0xbf7cbe793f733ec4,0xbf7e3d493f803dc9,0xbf39bf3e3f1d3f55,0xbf65bf043f513f22,0xbe60bf7d3d973f80,0xbefcbf673eb83f75,
0xbe95bf7b3dc93f80,0xbf22bf553ef13f6d,0xbf62bf0e3f463f35,0xbf7fbe483f753ec4,0xbf753e483f7f0000,0xbf463f0e3f62bec4,0xbef13f553f22bf35,0xbdc93f7b3e95bf6d,
0xbf753e483f7f8000,0xbf463f0e3f62bec4,0xbef13f553f22bf35,0xbdc93f7b3e95bf6d,0x3e953f7bbdc9bf80,0x3f223f55bef1bf6d,0x3f623f0ebf46bf35,0x3f7f3e48bf75bec4,
0xbe603f713ee6bf55,0x3e893f7dbcc9bf7f,0xbf6f3e793f7e0000,0xbf273f2c3f51bef1,0x3f7cbd49bf7fbe48,0x3f4abf04bf6a3e95,0x3f313f4ebefcbf6d,0x3f733edbbf58bf22,
0x3f7a3eacbf65bf0e,0x3f77be16bf80bdc9,0x3eb83f78bdfbbf80,0x3f423f3ebf13bf62,0xbe2fbf80bd973f7b,0xbf1dbf5c3ecf3f75,0x3f39bf18bf5f3ec4,0x3ea1bf67bf093f46,
0x3eacbf62bf183f35,0xbe79bf7fbd493f7b,0xbf3ebf463f043f6d,0xbf7dbe953f673f0e,0x3edb3f75be16bf80,0x3f5c3f22bf2cbf55,0x3f803dc9bf78bec4,0x3f4ebef1bf713e48,
0xbf71bef13f4e3f35,0xbf783dc93f803e48,0xbf2c3f223f5cbec4,0xbe163f753edbbf55,0x3f67be95bf7d8000,0x3f04bf46bf3e3f0e,0xbd49bf7fbe793f6d,0xbf18bf623eac3f7b,
0xbd973f783ecfbf55,0x3f133f67be89bf7f,0xbf7ebd493f7a3ec4,0xbf313f183f65be95,0xbea1bf7dbcc93f7b,0xbf58bf2c3f1d3f62,0x3f5fbeacbf7c0000,0x3eb8bf5cbf273f22,
0x3f7f3e79bf6abf0e,0x3f51bedbbf773dc9,0x3dfb3f803e60bf6d,0x3f393f4ebee6bf75,0xbf733e163f803e48,0xbf093f3e3f4abef1,0xbefcbf713e2f3f80,0xbf6fbf043f423f46,
0xbf0ebf6d3e483f80,0xbf7bbec43f553f35,0xbf553ec43f7b0000,0xbe483f6d3f0ebf35,0x3f0e3f6dbe48bf80,0x3f7b3ec4bf55bf35,0x3f55bec4bf7b0000,0x3e48bf6dbf0e3f35,
0xbf553ec43f7b8000,0xbe483f6d3f0ebf35,0x3f0e3f6dbe48bf80,0x3f7b3ec4bf55bf35,0x3f55bec4bf7b8000,0x3e48bf6dbf0e3f35,0xbf0ebf6d3e483f80,0xbf7bbec43f553f35,
0x3f423f4ebecfbf7b,0x3f7c3d49bf77bef1,0xbf4a3edb3f7a0000,0xbcc93f783ee6bf46,0xbf73bf043f393f55,0xbf583eac3f7e3dc9,0x3efcbf3ebf513ec4,0xbeb8bf7dbd973f75,
0x3f27bf18bf6a3e48,0xbe2fbf80be893f62,0x3f1d3f67be60bf80,0x3f803e79bf65bf22,0xbea13f5c3f31bf0e,0x3f093f71bdfbbf7f,0xbf5fbf2c3f133f6d,0xbf6f3e163f7f3e95,
0xbf80be953f5c3f35,0xbf183f223f67be48,0x3eac3f7f3e16bf6d,0x3f783ef1bf3ebf55,0x3f2c3f62be79bf80,0x3f7d3dc9bf71bf0e,0x3edbbf46bf4e3ec4,0xbf04bf753d493f7b,
0xbd493f753f04bf35,0x3f4e3f46bedbbf7b,0x3f71bdc9bf7dbec4,0x3e79bf62bf2c3f0e,0x3f3ebef1bf788000,0xbe16bf7fbeac3f55,0xbf67bf223f183f6d,0xbf5c3e953f803e48,
0x3f09bf2cbf653e48,0xbefcbf78bcc93f75,0x3ecf3f7d3dfbbf6d,0x3f7f3eacbf51bf46,0xbf7cbedb3f423f55,0xbf1d3f183f6fbdc9,0x3f31bf04bf770000,0xbea1bf80be603f62,
0xbf58bf3e3ee63f7b,0xbf5f3e793f803e95,0x3f6abe16bf7ebec4,0x3d97bf71bf133f22,0xbe2f3f673f27bf0e,0x3f4a3f4ebeb8bf7f,0xbf39bf5c3e893f80,0xbf733d493f7a3ef1,
0xbf46bf553e953f80,0xbf623e483f7f3ec4,0x3dc93f7b3ef1bf35,0x3f753f0ebf22bf6d,0x3f22bf0ebf750000,0xbef1bf7bbdc93f6d,0xbf7fbe483f623f35,0xbe953f553f46bec4,
0xbf223f0e3f758000,0x3ef13f7b3dc9bf6d,0x3f7f3e48bf62bf35,0x3e95bf55bf463ec4,0xbf46bf553e953f80,0xbf623e483f7f3ec4,0x3dc93f7b3ef1bf35,0x3f753f0ebf22bf6d,
0x3f6fbd49bf77bf0e,0xbd97bf78bf093f22,0xbf133f183f730000,0x3f1d3f71bcc9bf75,0x3f313f67bdfbbf7b,0x3f65be16bf7cbef1,0xbf7abf043f273f6d,0xbefc3f2c3f6abdc9,
0xbeb8bf80be893f55,0xbf7fbe793f583f46,0x3f513f4ebea1bf80,0x3f4abeacbf80be95,0x3f39bedbbf7ebe48,0xbee6bf7dbe2f3f62,0xbe603f5c3f42bec4,0x3f5f3f3ebecfbf7f,
0x3e793f7f3edbbf35,0x3f803e95bf4ebf55,0x3e16bf62bf3e3ec4,0xbf71bf223f043f7b,0x3f5c3f46beacbf80,0x3f2cbef1bf7dbe48,0xbf18bf75bd493f6d,0xbf673dc93f783f0e,
0x3f783dc9bf67bf35,0xbd49bf75bf183f0e,0xbf7dbef13f2c3f6d,0xbeac3f463f5cbe48,0x3f04bf22bf718000,0xbf3ebf623e163f7b,0xbf4e3e953f803ec4,0x3edb3f7f3e79bf55,
0xbf5f3e163f7a3f0e,0x3ecf3f803ea1bf46,0x3f42beacbf80bec4,0xbf13bf78bdfb3f62,0xbf1d3f043f7c3e48,0x3f393f67bd97bf75,0x3ee6bf2cbf6f0000,0xbf58bf4e3e893f7f,
0x3efc3f7d3e60bf55,0x3f6abd49bf73bf22,0xbf27bf71bcc93f6d,0xbf513e793f7e3ef1,0x3f4a3f5cbe2fbf7b,0x3f31bedbbf7fbe95,0xbf65bf3e3eb83f80,0xbf093f183f773dc9,
0xbf6dbf353ec43f80,0xbec43f353f6d0000,0x3f6d3f35bec4bf80,0x3ec4bf35bf6d0000,0xbf6dbf353ec43f80,0xbec43f353f6d0000,0x3f6d3f35bec4bf80,0x3ec4bf35bf6d0000,
0xbec43f353f6d8000,0x3f6d3f35bec4bf80,0x3ec4bf35bf6d8000,0xbf6dbf353ec43f80,0xbec43f353f6d8000,0x3f6d3f35bec4bf80,0x3ec4bf35bf6d8000,0xbf6dbf353ec43f80,
0x3dfbbf5cbf513e48,0xbf80bedb3f273f75,0xbea13f3e3f6a0000,0x3f7a3f18befcbf7f,0xbe89bf7dbf093f0e,0xbf6fbd493f653f46,0x3d973f713f31bec4,0x3f7c3e79bf4abf62,
0xbf7ebf043f133f7b,0xbcc93f673f42be95,0x3f733f2cbecfbf80,0x3e60bf4ebf5f3dc9,0xbf77be163f583f55,0x3eb83f803ee6bf22,0x3f7f3eacbf39bf6d,0xbe2fbf78bf1d3ef1,
0x3f5cbdc9bf71bf35,0xbf2cbf75be163f55,0xbf183ef13f803ec4,0x3f673f46be79bf7b,0x3f783f22bedbbf80,0x3d49bf62bf4e3e48,0xbf7dbe953f3e3f6d,0x3eac3f7f3f04bf0e,
0xbf04bf7fbeac3f35,0xbf3e3e953f7d3f0e,0x3f4e3f62bd49bf6d,0x3edbbf22bf78be48,0x3e79bf46bf678000,0xbf80bef13f183f7b,0x3e163f753f2cbec4,0x3f713dc9bf5cbf55,
0x3f803edbbf1dbf7b,0xbea1bf7dbf133ef1,0xbf58bf5c3d973f6d,0xbe893f3e3f6f3dc9,0x3ecf3f803efcbf0e,0x3f42be79bf7abf22,0x3e2fbf4ebf650000,0xbf7ebeac3f313f75,
0xbcc9bf67bf4a3e48,0xbf73be163f513f62,0xbf093f043f7f3ec4,0x3f773f2cbeb8bf7f,0x3f6a3d49bf5fbf55,0xbf27bf78be603f46,0xbf7cbf183ee63f80,0x3dfb3f713f39be95,
0xbf7fbf0e3ef13f80,0x3e953f7b3f22bec4,0x3f46be48bf75bf35,0xbf62bf553dc93f6d,0xbdc93f553f620000,0x3f753e48bf46bf6d,0xbf22bf7bbe953f35,0xbef13f0e3f7f3ec4,
0xbdc93f553f628000,0x3f753e48bf46bf6d,0xbf22bf7bbe953f35,0xbef13f0e3f7f3ec4,0x3f7f3f0ebef1bf80,0xbe95bf7bbf223ec4,0xbf463e483f753f35,0x3f623f55bdc9bf6d,
0xbf51bf67bd973f55,0xbdfb3f4e3f6a3dc9,0xbcc93f5c3f5f0000,0x3f653d49bf58bf62,0xbe603f3e3f733e48,0x3f773e79bf39bf75,0x3f6f3e16bf4abf6d,0xbf42bf71be2f3f46,
0xbf133edb3f7f3f0e,0x3f7e3f18becfbf7f,0x3f803f04befcbf80,0xbee6bf80bf093ef1,0x3f7a3f2cbea1bf7b,0xbe89bf78bf313e95,0xbeb8bf7dbf1d3ec4,0xbf273eac3f7c3f22,
0xbf3ebf75be793f35,0xbe163f463f713e48,0x3f673dc9bf4ebf6d,0xbf5cbf62bd493f55,0x3f803ef1bf04bf80,0xbf18bf7fbedb3f0e,0xbeac3f223f7d3ec4,0x3f783e95bf2cbf7b,
0xbf2c3e953f783f35,0x3f7d3f22beacbf7b,0xbedbbf7fbf183ec4,0xbf043ef13f803f0e,0xbd49bf62bf5c8000,0xbf4e3dc93f673f55,0x3f713f46be16bf6d,0xbe79bf75bf3e3e48,
0xbf65bf5cbcc93f55,0x3e603f713f4abdc9,0xbe893f2c3f7c3ec4,0x3f6a3e16bf42bf75,0x3f7f3f18beb8bf7b,0xbf13bf80befc3ef1,0xbdfbbf67bf580000,0xbf313e793f733f46,
0xbee63f043f803f0e,0x3f7a3eacbf1dbf7f,0x3f773f3ebe2fbf6d,0xbecfbf7dbf273e95,0x3d97bf4ebf6fbe48,0xbf513d493f5f3f62,0xbf7ebedb3f093f80,0x3f393f783ea1bf22,
0xbf7bbec43f0e3f80,0x3f553f6d3e48bf35,0xbe48bf6dbf550000,0xbf0e3ec43f7b3f35,0x3f7b3ec4bf0ebf80,0xbf55bf6dbe483f35,0x3e483f6d3f550000,0x3f0ebec4bf7bbf35,
0x3e483f6d3f558000,0x3f0ebec4bf7bbf35,0xbf7bbec43f0e3f80,0x3f553f6d3e48bf35,0xbe48bf6dbf558000,0xbf0e3ec43f7b3f35,0x3f7b3ec4bf0ebf80,0xbf55bf6dbe483f35,
0xbf65be163f393f7b,0x3f7a3f3ebdfbbf62,0x3e893f713f510000,0x3ecfbf04bf7fbf22,0x3f27be79bf6fbf55,0xbf7cbedb3efc3f7f,0xbf1dbf80bf093ec4,0xbcc93f4e3f733e95,
0x3ee63f7d3f31be48,0x3e60bf2cbf7ebef1,0x3f773eacbf13bf80,0xbf6abf5cbd973f46,0xbf42bf78beb83f0e,0x3e2f3f673f5f3dc9,0xbf4a3d493f583f6d,0x3f803f18bea1bf75,
0xbedb3ef13f7d3f35,0x3f5c3dc9bf3ebf7b,0xbf80bf223e793f6d,0x3f4e3f753eacbf0e,0x3f713e95bf18bf80,0xbf78bf463d493f55,0x3f2c3f7f3f04bec4,0xbe16bf62bf67be48,
0x3f673f623e16bf35,0xbf04bf7fbf2c3e48,0xbd493f463f783ec4,0x3f18be95bf71bf55,0xbeacbf75bf4e8000,0xbe793f223f803f0e,0x3f3ebdc9bf5cbf6d,0xbf7dbef13edb3f7b,
0x3f133f803f27be48,0xbdfbbf5cbf6fbe95,0x3f803f18be89bf6d,0xbf65bf67be603f22,0x3f09beacbf73bf55,0xbf5fbe163f313f7f,0xbecfbf78bf4a0000,0xbd973f3e3f7c3ef1,
0x3f513d49bf42bf7b,0xbf7ebf043eb83f75,0xbcc9bf4ebf77bec4,0xbee63edb3f7a3f46,0xbf58bf71bea13f0e,0x3efc3f7d3f39bdc9,0xbf6abe793f1d3f80,0x3f7f3f2cbe2fbf62,
0xbf62be483f223f80,0x3f7f3f0ebe95bf6d,0xbf75bf55bdc93f35,0x3f463f7b3ef1bec4,0xbef1bf7bbf460000,0x3dc93f553f753ec4,0x3e95bf0ebf7fbf35,0xbf223e483f623f6d,
0x3ef13f7b3f468000,0xbdc9bf55bf75bec4,0xbe953f0e3f7f3f35,0x3f22be48bf62bf6d,0xbf62be483f223f80,0x3f7f3f0ebe95bf6d,0xbf75bf55bdc93f35,0x3f463f7b3ef1bec4,
0xbcc93f3e3f7e3f0e,0x3ea1bf04bf7cbf46,0x3f093f7d3f420000,0xbe89bf67bf6abe95,0xbf6fbeac3efc3f7b,0x3f7f3f18be60bf62,0xbf133e793f653f6d,0x3f4a3d49bf39bf7f,
0x3f803f2cbdfbbf55,0xbf73bf5cbe2f3f22,0x3f583e16bf27bf80,0xbf77bedb3ecf3f75,0x3eb83f713f5f3e48,0xbd97bf4ebf7abef1,0x3f513f783ee6bec4,0xbf1dbf80bf313dc9,
0x3f7d3f463d49bf35,0xbf71bf62be793f0e,0x3f5c3f753edbbec4,0xbf3ebf7fbf183e48,0x3f4e3dc9bf2cbf80,0xbf67be953f043f7b,0x3f783ef1beacbf6d,0xbf80bf223e163f55,
0x3e16bf22bf80bf35,0xbeac3ef13f783f55,0x3f04be95bf67bf6d,0xbf2c3dc93f4e3f7b,0xbf18bf7fbf3e8000,0x3edb3f753f5c3e48,0xbe79bf62bf71bec4,0x3d493f463f7d3f0e,
0xbdfbbf4ebf7cbf0e,0x3cc93f3e3f7f3f22,0xbea1bf67bf6fbec4,0x3e603f5c3f773ef1,0xbefcbf78bf58be48,0x3ecf3f713f653e95,0xbf27bf80bf390000,0x3f133f7d3f4a3dc9,
0xbf7ebf183e2f3f55,0x3f803f2cbd97bf46,0xbf73bedb3eb83f6d,0x3f7a3f04be89bf62,0xbf5fbe793f093f7b,0x3f6a3eacbee6bf75,0xbf42bd493f313f80,0x3f513e16bf1dbf7f,
0x3f350000bf353f80,0xbf3500003f35bf80,0x3f350000bf353f80,0xbf3500003f35bf80,0x3f350000bf353f80,0xbf3500003f35bf80,0x3f350000bf353f80,0xbf3500003f35bf80,
0xbf353f80bf358000,0x3f35bf803f358000,0xbf353f80bf358000,0x3f35bf803f358000,0xbf353f80bf358000,0x3f35bf803f358000,0xbf353f80bf358000,0x3f35bf803f358000,
0xbefc3f5c3f09bf55,0xbecf3f673ee6bf62,0xbf273f3e3f31bf35,0xbf133f4e3f1dbf46,0xbdfb3f7d3e2fbf7b,0xbcc93f803d97bf7f,0xbea13f713eb8bf6d,0xbe603f783e89bf75,
0x3f5f3f04bf58bf0e,0x3f6a3edbbf65bef1,0x3f423f2cbf39bf35,0x3f513f18bf4abf22,0x3f7e3e16bf7cbe48,0x3f803d49bf7fbdc9,0x3f733eacbf6fbec4,0x3f7a3e79bf77be95,
0x3f18bf46bf2c3f35,0x3edbbf62bf043f55,0x3e79bf75beac3f6d,0x3d49bf7fbe163f7b,0x3f7dbdc9bf800000,0x3f71be95bf783e48,0x3f5cbef1bf673ec4,0x3f3ebf22bf4e3f0e,
0xbf4ebf223f3e3f35,0xbf67bef13f5c3f0e,0xbf78be953f713ec4,0xbf80bdc93f7d3e48,0xbe16bf7f3d493f80,0xbeacbf753e793f7b,0xbf04bf623edb3f6d,0xbf2cbf463f183f55,
0xbeb83f673efcbf55,0xbd973f7d3e60bf75,0xbf513f043f65bec4,0xbf1d3f3e3f39bf22,0xbf80bd493f7e3e48,0xbf733e793f7cbdc9,0xbf58bf183f423f35,0xbf77beac3f6a3ef1,
0x3f6f3edbbf5fbf0e,0x3f7f3e16bf7abe95,0x3f133f5cbee6bf6d,0x3f4a3f2cbf31bf46,0x3cc93f803dfbbf7b,0x3ea13f78be2fbf7f,0xbf093f4e3f27bf35,0xbe893f713ecfbf62,
0x3e953f7bbdc9bf80,0x3f223f55bef1bf6d,0x3f623f0ebf46bf35,0x3f7f3e48bf75bec4,0x3f75be48bf7f0000,0x3f46bf0ebf623ec4,0x3ef1bf55bf223f35,0x3dc9bf7bbe953f6d,
0x3f75be48bf7f8000,0x3f46bf0ebf623ec4,0x3ef1bf55bf223f35,0x3dc9bf7bbe953f6d,0xbe95bf7b3dc93f80,0xbf22bf553ef13f6d,0xbf62bf0e3f463f35,0xbf7fbe483f753ec4,
0xbf09bf673ea13f7b,0xbf5fbf183f393f46,0x3ecfbf5cbf1d3f35,0xbd97bf80be2f3f75,0xbf133f3e3f42bf0e,0xbdfb3f783eb8bf62,0xbf80be163f773ec4,0xbf653eac3f7abdc9,
0xbf583edb3f73be48,0xbefc3f4e3f31bf22,0xbf6abf043f4a3f35,0xbf7fbd493f7c3e95,0x3f513f2cbf27bf55,0x3f7e3e79bf6fbef1,0xbcc93f7d3e89bf6d,0x3ee63f71be60bf7f,
0x3f713ef1bf4ebf35,0x3f78bdc9bf80be48,0x3f2cbf22bf5c3ec4,0x3e16bf75bedb3f55,0xbf673e953f7d0000,0xbf043f463f3ebf0e,0x3d493f7f3e79bf6d,0x3f183f62beacbf7b,
0x3eacbf62bf183f35,0xbe79bf7fbd493f7b,0xbf3ebf463f043f6d,0xbf7dbe953f673f0e,0x3edb3f75be16bf80,0x3f5c3f22bf2cbf55,0x3f803dc9bf78bec4,0x3f4ebef1bf713e48,
0xbf423f043f6fbe48,0xbe2f3f713efcbf46,0xbf4abf3e3f093f6d,0xbf80be163f733ef1,0x3ee6bf4ebf393f0e,0xbe60bf80bdfb3f75,0x3f773edbbf51bf35,0x3f6abe79bf7fbdc9,
0x3f273f5cbeb8bf7b,0x3f7c3eacbf5fbf22,0xbf1d3f2c3f58bec4,0x3cc93f7d3ea1bf62,0xbf65bf183f313f55,0xbf7a3d493f7e3e95,0x3e89bf67bf133f35,0xbecfbf783d973f7f,
0xbf0ebf6d3e483f80,0xbf7bbec43f553f35,0xbf553ec43f7b0000,0xbe483f6d3f0ebf35,0x3f0e3f6dbe48bf80,0x3f7b3ec4bf55bf35,0x3f55bec4bf7b0000,0x3e48bf6dbf0e3f35,
0xbf553ec43f7b8000,0xbe483f6d3f0ebf35,0x3f0e3f6dbe48bf80,0x3f7b3ec4bf55bf35,0x3f55bec4bf7b8000,0x3e48bf6dbf0e3f35,0xbf0ebf6d3e483f80,0xbf7bbec43f553f35,
0x3f7f3e16bf6fbf0e,0x3f13bf2cbf5f3e95,0xbdfb3f713f09bf35,0x3f313f5cbea1bf7f,0xbf653e793f803e48,0xbe603f673f1dbf22,0xbe89bf80be2f3f6d,0xbf6abf183f273f62,
0xbd97bf7dbeb83f55,0xbf51bf3e3efc3f75,0x3f7e3eacbf58bf35,0x3f39bf04bf733dc9,0x3ee63f78bcc9bf7b,0x3f7a3edbbf4abf46,0xbf773d493f7c3ec4,0xbecf3f4e3f42bef1,
0xbd493f753f04bf35,0x3f4e3f46bedbbf7b,0x3f71bdc9bf7dbec4,0x3e79bf62bf2c3f0e,0x3f3ebef1bf780000,0xbe16bf7fbeac3f55,0xbf67bf223f183f6d,0xbf5c3e953f803e48,
0x3f803e95bf5cbf35,0x3f18bf22bf673e48,0xbeacbf7fbe163f6d,0xbf78bef13f3e3f55,0xbf2cbf623e793f80,0xbf7dbdc93f713f0e,0xbedb3f463f4ebec4,0x3f043f75bd49bf7b,
0xbf7abd493f733f0e,0xbe893f5c3f39bef1,0x3eb8bf4ebf4a3ec4,0xbf27bf673e2f3f7f,0x3f133f71bd97bf7b,0x3f7e3e16bf6abf22,0xbf80be793f5f3f35,0xbee63f3e3f58be95,
0x3e603f803ea1bf55,0x3f773f04bf31bf62,0xbf6fbf183f1d3f6d,0xbf423edb3f7c3dc9,0x3f51beacbf7fbe48,0xbdfbbf7dbecf3f46,0x3cc93f783efcbf35,0x3f653f2cbf09bf75,
0x3f463f55be95bf80,0x3f62be48bf7fbec4,0xbdc9bf7bbef13f35,0xbf75bf0e3f223f6d,0xbf223f0e3f750000,0x3ef13f7b3dc9bf6d,0x3f7f3e48bf62bf35,0x3e95bf55bf463ec4,
0x3f22bf0ebf758000,0xbef1bf7bbdc93f6d,0xbf7fbe483f623f35,0xbe953f553f46bec4,0x3f463f55be95bf80,0x3f62be48bf7fbec4,0xbdc9bf7bbef13f35,0xbf75bf0e3f223f6d,
0xbecf3f3e3f5fbe48,0x3f423f5cbe60bf7f,0xbe2fbf7dbee63f35,0xbf7ebedb3f393f62,0xbf80beac3f4a3f55,0xbea13f4e3f51be95,0x3f58be79bf7fbec4,0xbe89bf80beb83f46,
0x3f6a3f2cbefcbf7b,0x3f27bf04bf7abdc9,0xbf7cbe163f653f35,0xbdfb3f673f31bef1,0xbcc93f713f1dbf0e,0x3f733f18bf13bf75,0xbf09bf78bd973f6d,0xbf77bd493f6f3f22,
0xbf78bdc93f673f35,0x3d493f753f18bf0e,0x3f7d3ef1bf2cbf6d,0x3eacbf46bf5c3e48,0xbf043f223f710000,0x3f3e3f62be16bf7b,0x3f4ebe95bf80bec4,0xbedbbf7fbe793f55,
0x3e793f7f3edbbf35,0x3f803e95bf4ebf55,0x3e16bf62bf3e3ec4,0xbf71bf223f043f7b,0x3f5c3f46beacbf80,0x3f2cbef1bf7dbe48,0xbf18bf75bd493f6d,0xbf673dc93f783f0e,
0xbf77bf183f093f7b,0xbeb83f3e3f65bdc9,0x3f7f3edbbf31bf6d,0x3e2fbf5cbf4a3e95,0xbf7ebe793f513f55,0x3cc93f713f27bef1,0x3f733d49bf6abf35,0xbe60bf7dbefc3f22,
0xbe893f4e3f58be48,0x3f6f3f2cbee6bf7f,0x3d97bf67bf393ec4,0xbf7cbf043f1d3f75,0x3dfb3f783f13bf0e,0x3f803eacbf42bf62,0xbea1bf80becf3f35,0xbf7abe163f5f3f46,
0xbf6dbf353ec43f80,0xbec43f353f6d0000,0x3f6d3f35bec4bf80,0x3ec4bf35bf6d0000,0xbf6dbf353ec43f80,0xbec43f353f6d0000,0x3f6d3f35bec4bf80,0x3ec4bf35bf6d0000,
0xbec43f353f6d8000,0x3f6d3f35bec4bf80,0x3ec4bf35bf6d8000,0xbf6dbf353ec43f80,0xbec43f353f6d8000,0x3f6d3f35bec4bf80,0x3ec4bf35bf6d8000,0xbf6dbf353ec43f80,
0xbf1dbf78be2f3f55,0xbf393eac3f7f3ef1,0x3ee63f803eb8bf35,0x3f58be16bf77bf22,0xbf5fbf4e3e603f7b,0xbecf3f2c3f733dc9,0x3f423f67bcc9bf6d,0x3f13bf04bf7ebe95,
0xbf4a3e793f7c3f0e,0x3f313f713d97bf62,0x3f65bd49bf6fbf35,0xbf09bf7dbe893f46,0xbefc3f183f7a3e48,0x3f6a3f3ebea1bf7f,0x3f27bedbbf80bec4,0xbf51bf5c3dfb3f75,
0xbf04bf7fbeac3f35,0xbf3e3e953f7d3f0e,0x3f4e3f62bd49bf6d,0x3edbbf22bf78be48,0x3e79bf46bf670000,0xbf80bef13f183f7b,0x3e163f753f2cbec4,0x3f713dc9bf5cbf55,
0xbf5c3dc93f713f35,0x3f2c3f753e16bf55,0x3f18bef1bf80bec4,0xbf67bf463e793f7b,0xbf78bf223edb3f80,0xbd493f623f4ebe48,0x3f7d3e95bf3ebf6d,0xbeacbf7fbf043f0e,
0xbf39bf71bdfb3f55,0xbee63f183f7c3e95,0x3e603f783f27bec4,0x3f5fbd49bf6abf46,0x3eb8bf2cbf77be48,0xbf7fbf043f093f7f,0xbf513e163f733f35,0x3f4a3f673cc9bf62,
0xbf313eac3f7e3f0e,0x3f653f4ebe2fbf75,0x3f7a3e79bf42bf6d,0xbefcbf80becf3f22,0xbf6fbf3e3e893f7b,0xbd973f5c3f58bdc9,0x3f133f7d3ea1bf35,0x3f1dbedbbf80bef1,
0x3f7f3f0ebef1bf80,0xbe95bf7bbf223ec4,0xbf463e483f753f35,0x3f623f55bdc9bf6d,0x3dc9bf55bf620000,0xbf75be483f463f6d,0x3f223f7b3e95bf35,0x3ef1bf0ebf7fbec4,
0x3dc9bf55bf628000,0xbf75be483f463f6d,0x3f223f7b3e95bf35,0x3ef1bf0ebf7fbec4,0xbf7fbf0e3ef13f80,0x3e953f7b3f22bec4,0x3f46be48bf75bf35,0xbf62bf553dc93f6d,
0x3f7c3eacbf27bf7b,0xbf1dbf7dbeb83f22,0xbf31bf78be893f35,0xbea13f2c3f7a3e95,0xbf09bf80bee63f0e,0xbefc3f043f803ef1,0xbecf3f183f7e3ec4,0x3f7f3edbbf13bf7f,
0xbe2fbf71bf423e48,0xbf4a3e163f6f3f46,0xbf393e793f773f35,0x3f733f3ebe60bf75,0xbf583d493f653f55,0x3f5f3f5cbcc9bf62,0x3f6a3f4ebdfbbf6d,0xbd97bf67bf513dc9,
0x3f2cbe95bf78bf35,0xbf7dbf223eac3f7b,0x3edb3f7f3f18bec4,0x3f04bef1bf80bf0e,0x3d493f623f5c0000,0x3f4ebdc9bf67bf55,0xbf71bf463e163f6d,0x3e793f753f3ebe48,
0xbf3ebf75be793f35,0xbe163f463f713e48,0x3f673dc9bf4ebf6d,0xbf5cbf62bd493f55,0x3f803ef1bf04bf80,0xbf18bf7fbedb3f0e,0xbeac3f223f7d3ec4,0x3f783e95bf2cbf7b,
0xbea1bf78bf393e48,0xbf093edb3f7e3f22,0xbf5fbd493f513f6d,0x3f6f3f4ebd97bf62,0x3f273f7d3ecfbf0e,0x3e2fbf3ebf77be95,0x3f1dbeacbf7abf35,0xbf80bf043ee63f7f,
0xbf73be793f313f7b,0x3f583f673dfbbf46,0x3efc3f803f13bec4,0x3eb8bf18bf7fbef1,0x3f42be16bf6abf55,0xbf7cbf2c3e893f75,0xbf4abf71be603f35,0x3cc93f5c3f653dc9,
0xbf7bbec43f0e3f80,0x3f553f6d3e48bf35,0xbe48bf6dbf550000,0xbf0e3ec43f7b3f35,0x3f7b3ec4bf0ebf80,0xbf55bf6dbe483f35,0x3e483f6d3f550000,0x3f0ebec4bf7bbf35,
0x3e483f6d3f558000,0x3f0ebec4bf7bbf35,0xbf7bbec43f0e3f80,0x3f553f6d3e48bf35,0xbe48bf6dbf558000,0xbf0e3ec43f7b3f35,0x3f7b3ec4bf0ebf80,0xbf55bf6dbe483f35,
0xbea13f183f803f0e,0x3f583d49bf4abf75,0x3f5f3f673e2fbf35,0xbeb8bf78bf423dc9,0xbd97bf5cbf6abe48,0xbf133eac3f773f46,0xbf7ebf2c3e603f6d,0x3f313f7d3ee6bef1,
0x3f733f4ebcc9bf55,0xbf09bf80bf1d3e95,0x3efcbedbbf7cbf35,0xbf6fbe793f273f7f,0xbf7fbf043ecf3f7b,0x3f513f713e89bf22,0xbdfb3f3e3f7a3ec4,0x3f39be16bf65bf62,
0x3f673f623e16bf35,0xbf04bf7fbf2c3e48,0xbd493f463f783ec4,0x3f18be95bf71bf55,0xbeacbf75bf4e0000,0xbe793f223f803f0e,0x3f3ebdc9bf5cbf6d,0xbf7dbef13edb3f7b,
0x3edbbef1bf7dbf35,0xbf5cbdc93f3e3f7b,0x3f803f22be79bf6d,0xbf4ebf75beac3f0e,0xbf71be953f183f80,0x3f783f46bd49bf55,0xbf2cbf7fbf043ec4,0x3e163f623f673e48,
0x3e2fbf2cbf7fbf0e,0xbf1d3e793f6a3f62,0xbf39bf7dbefc3ec4,0x3ea13f713f583dc9,0xbf7abedb3ee63f7b,0x3f773f4e3cc9bf46,0xbeb83f043f7e3f35,0x3f42bd49bf51bf75,
0xbf7cbf3e3d973f55,0x3f4a3f783ecfbef1,0xbf313e163f5f3f6d,0x3f733eacbf09bf7f,0x3e603f673f653e48,0x3e89bf18bf80bf22,0x3f6f3f5c3dfbbf35,0xbf27bf80bf133e95,
0x3f623e48bf22bf80,0xbf7fbf0e3e953f6d,0x3f753f553dc9bf35,0xbf46bf7bbef13ec4,0x3ef13f7b3f460000,0xbdc9bf55bf75bec4,0xbe953f0e3f7f3f35,0x3f22be48bf62bf6d,
0xbef1bf7bbf468000,0x3dc93f553f753ec4,0x3e95bf0ebf7fbf35,0xbf223e483f623f6d,0x3f623e48bf22bf80,0xbf7fbf0e3e953f6d,0x3f753f553dc9bf35,0xbf46bf7bbef13ec4,
0xbf31bf80bf1d3e48,0x3ee63f783f513dc9,0xbf7abf4ebd973f35,0x3f5f3f713eb8bef1,0x3ecfbedbbf77bf55,0xbf273e163f583f75,0xbe2fbf5cbf73bec4,0xbdfb3f2c3f803f22,
0xbf393d493f4a3f7b,0x3f653e79bf13bf7f,0xbe603f183f7f3f35,0x3efcbeacbf6fbf62,0xbf6abf67be893f0e,0x3f423f7d3f09be95,0xbf7cbf043ea13f6d,0x3f7e3f3ebcc9bf46,
0xbe163f223f803f35,0x3eacbef1bf78bf55,0xbf043e953f673f6d,0x3f2cbdc9bf4ebf7b,0x3f183f7f3f3e0000,0xbedbbf75bf5cbe48,0x3e793f623f713ec4,0xbd49bf46bf7dbf0e,
0x3f7d3f463d49bf35,0xbf71bf62be793f0e,0x3f5c3f753edbbec4,0xbf3ebf7fbf183e48,0x3f4e3dc9bf2cbf80,0xbf67be953f043f7b,0x3f783ef1beacbf6d,0xbf80bf223e163f55,
0x3f1dbe16bf51bf7b,0xbf313d493f423f7f,0x3ee6beacbf6abf6d,0xbf093e793f5f3f75,0x3e89bf04bf7abf55,0xbeb83edb3f733f62,0x3d97bf2cbf80bf35,0xbe2f3f183f7e3f46,
0xbf4abf7dbf133e48,0x3f393f803f27bdc9,0xbf65bf71becf3ec4,0x3f583f783efcbe95,0xbf77bf5cbe603f0e,0x3f6f3f673ea1bef1,0xbf7fbf3ebcc93f35,0x3f7c3f4e3dfbbf22,
0x3f003f003f003f00,0x3f003f003f003f00,0x3f003f003f003f00,0x3f003f003f003f00,0x3f003f003f003f00,0x3f003f003f003f00,0x3f003f003f003f00,0x3f003f003f003f00,
0xbf003f00bf003f00,0xbf003f00bf003f00,0xbf003f00bf003f00,0xbf003f00bf003f00,0xbf003f00bf003f00,0xbf003f00bf003f00,0xbf003f00bf003f00,0xbf003f00bf003f00,
0xbf77bf78bf7abf7b,0xbf6fbf71bf73bf75,0xbf7fbf80bf80bf80,0xbf7cbf7dbf7ebf7f,0xbf4abf4ebf51bf55,0xbf39bf3ebf42bf46,0xbf65bf67bf6abf6d,0xbf58bf5cbf5fbf62,
0x3e893e793e603e48,0x3eb83eac3ea13e95,0x3d973d493cc98000,0x3e2f3e163dfb3dc9,0x3f1d3f183f133f0e,0x3f313f2c3f273f22,0x3ee63edb3ecf3ec4,0x3f093f043efc3ef1,
0x3f183f223f2c3f35,0x3edb3ef13f043f0e,0x3e793e953eac3ec4,0x3d493dc93e163e48,0x3f7d3f7f3f803f80,0x3f713f753f783f7b,0x3f5c3f623f673f6d,0x3f3e3f463f4e3f55,
0xbf4ebf46bf3ebf35,0xbf67bf62bf5cbf55,0xbf78bf75bf71bf6d,0xbf80bf7fbf7dbf7b,0xbe16bdc9bd498000,0xbeacbe95be79be48,0xbf04bef1bedbbec4,0xbf2cbf22bf18bf0e,
0x3ecf3eac3e893e48,0x3f273f183f093ef1,0xbe2fbe79bea1bec4,0x3dfb3d49bcc9bdc9,0xbf31bf3ebf4abf55,0xbee6bf04bf13bf22,0xbf7abf7dbf7fbf80,0xbf5fbf67bf6fbf75,
0x3f6a3f713f773f7b,0x3f423f4e3f583f62,0x3f7c3f783f733f6d,0x3f7e3f803f803f7f,0x3f393f2c3f1d3f0e,0x3f653f5c3f513f46,0x3e603e163d978000,0x3efc3edb3eb83e95,
0x3f753f7b3f7f3f80,0x3f463f553f623f6d,0x3ef13f0e3f223f35,0x3dc93e483e953ec4,0xbe95be48bdc90000,0xbf22bf0ebef1bec4,0xbf62bf55bf46bf35,0xbf7fbf7bbf75bf6d,
0xbe95be48bdc98000,0xbf22bf0ebef1bec4,0xbf62bf55bf46bf35,0xbf7fbf7bbf75bf6d,0xbf75bf7bbf7fbf80,0xbf46bf55bf62bf6d,0xbef1bf0ebf22bf35,0xbdc9be48be95bec4,
0xbe60beacbee6bf0e,0x3e893e163cc9bdc9,0xbf6fbf78bf7ebf80,0xbf27bf3ebf51bf62,0x3f7c3f803f7f3f7b,0x3f4a3f5c3f6a3f75,0x3f313f183efc3ec4,0x3f733f673f583f46,
0x3f7a3f713f653f55,0x3f773f7d3f803f7f,0x3eb83e793dfb8000,0x3f423f2c3f133ef1,0xbe2fbd493d973e48,0xbf1dbf04becfbe95,0x3f393f4e3f5f3f6d,0x3ea13edb3f093f22,
0xbf71bf62bf4ebf35,0xbf78bf7fbf80bf7b,0xbf2cbf46bf5cbf6d,0xbe16be95bedbbf0e,0x3f673f753f7d3f80,0x3f043f223f3e3f55,0xbd493dc93e793ec4,0xbf18bef1beacbe48,
0xbeacbef1bf18bf35,0x3e793dc9bd49be48,0x3f3e3f223f043ec4,0x3f7d3f753f673f55,0xbedbbe95be168000,0xbf5cbf46bf2cbf0e,0xbf80bf7fbf78bf6d,0xbf4ebf62bf71bf7b,
0x3d973e793ecf3f0e,0xbf13bedbbe89bdc9,0x3f7e3f803f7a3f6d,0x3f313f4e3f653f75,0x3ea13e16bcc9be48,0x3f583f3e3f1d3ef1,0xbf5fbf71bf7cbf80,0xbeb8bf04bf27bf46,
0xbf7fbf78bf6abf55,0xbf51bf67bf77bf7f,0xbdfb3d493e603ec4,0xbf39bf18bee6be95,0x3f733f7d3f803f7b,0x3f093f2c3f4a3f62,0x3efc3eac3e2f8000,0x3f6f3f5c3f423f22,
0x3f553f6d3f7b3f80,0x3e483ec43f0e3f35,0xbf0ebec4be480000,0xbf7bbf6dbf55bf35,0xbf55bf6dbf7bbf80,0xbe48bec4bf0ebf35,0x3f0e3ec43e480000,0x3f7b3f6d3f553f35,
0xbf0ebec4be488000,0xbf7bbf6dbf55bf35,0xbf55bf6dbf7bbf80,0xbe48bec4bf0ebf35,0x3f0e3ec43e488000,0x3f7b3f6d3f553f35,0x3f553f6d3f7b3f80,0x3e483ec43f0e3f35,
0x3f423f183ecf3e48,0x3f7c3f803f773f62,0xbf4abf67bf7abf80,0xbcc9be79bee6bf22,0xbf73bf5cbf39bf0e,0xbf58bf71bf7ebf7f,0x3efc3f2c3f513f6d,0xbeb8be163d973e95,
0x3f273f4e3f6a3f7b,0xbe2f3d493e893ef1,0x3f1d3edb3e608000,0x3f803f783f653f46,0xbea1bf04bf31bf55,0x3f093eac3dfbbdc9,0xbf5fbf3ebf13bec4,0xbf6fbf7dbf7fbf75,
0xbd49be95bf04bf35,0x3f4e3f223edb3e48,0x3f713f7f3f7d3f6d,0x3e793ef13f2c3f55,0x3f3e3f623f783f80,0xbe163dc93eac3f0e,0xbf67bf46bf18bec4,0xbf5cbf75bf80bf7b,
0x3f803f753f5c3f35,0x3f183f463f673f7b,0xbeacbdc93e163ec4,0xbf78bf62bf3ebf0e,0xbf2cbef1be798000,0xbf7dbf7fbf71bf55,0xbedbbf22bf4ebf6d,0x3f043e953d49be48,
0xbf09bf3ebf65bf7b,0x3efc3e79bcc9be95,0xbecfbe163dfb3ec4,0xbf7fbf71bf51bf22,0x3f7c3f673f423f0e,0x3f1d3f4e3f6f3f7f,0xbf31bf5cbf77bf80,0x3ea13d49be60bef1,
0x3f583f2c3ee63e48,0x3f5f3f783f803f75,0xbf6abf7dbf7ebf6d,0xbd97beacbf13bf46,0x3e2f3edb3f273f55,0xbf4abf18beb8bdc9,0x3f393f043e898000,0x3f733f803f7a3f62,
0x3f223f553f753f80,0xbef1be483dc93ec4,0xbf7fbf7bbf62bf35,0xbe95bf0ebf46bf6d,0x3f463f0e3e950000,0x3f623f7b3f7f3f6d,0xbdc93e483ef13f35,0xbf75bf55bf22bec4,
0xbf46bf0ebe958000,0xbf62bf7bbf7fbf6d,0x3dc9be48bef1bf35,0x3f753f553f223ec4,0x3f223f553f753f80,0xbef1be483dc93ec4,0xbf7fbf7bbf62bf35,0xbe95bf0ebf46bf6d,
0x3f6f3f803f773f55,0xbd973e793f093f46,0xbf13bf4ebf73bf80,0x3f1d3eac3cc9be95,0x3f313edb3dfbbe48,0x3f653f7d3f7c3f62,0xbf7abf5cbf27bec4,0xbefcbf3ebf6abf7f,
0xbeb8bd493e893f0e,0xbf7fbf78bf58bf22,0x3f513f183ea18000,0x3f4a3f713f803f75,0x3f393f673f7e3f7b,0xbee6be163e2f3ef1,0xbe60bf04bf42bf6d,0x3f5f3f2c3ecf3dc9,
0x3f783f7f3f673f35,0xbd493e953f183f55,0xbf7dbf62bf2cbec4,0xbeacbf22bf5cbf7b,0x3f043f463f713f80,0xbf3ebef1be163e48,0xbf4ebf75bf80bf6d,0x3edb3dc9be79bf0e,
0xbe793dc93edb3f35,0xbf80bf75bf4ebf0e,0xbe16bef1bf3ebf6d,0x3f713f463f043e48,0xbf5cbf22beac8000,0xbf2cbf62bf7dbf7b,0x3f183e95bd49bec4,0x3f673f7f3f783f55,
0x3f5f3f7d3f7a3f55,0xbecfbd493ea13f22,0xbf42bf71bf80bf6d,0x3f133e79bdfbbef1,0x3f1d3f5c3f7c3f7b,0xbf39bedbbd973e95,0xbee6bf3ebf6fbf80,0x3f583f183e89bdc9,
0xbefcbe163e603f0e,0xbf6abf80bf73bf46,0x3f273eacbcc9bec4,0x3f513f783f7e3f62,0xbf4abf04be2f3e48,0xbf31bf67bf7fbf75,0x3f653f2c3eb88000,0x3f093f4e3f773f7f,
0x3ec43f353f6d3f80,0xbf6dbf35bec40000,0xbec4bf35bf6dbf80,0x3f6d3f353ec40000,0x3ec43f353f6d3f80,0xbf6dbf35bec40000,0xbec4bf35bf6dbf80,0x3f6d3f353ec40000,
0xbf6dbf35bec48000,0xbec4bf35bf6dbf80,0x3f6d3f353ec48000,0x3ec43f353f6d3f80,0xbf6dbf35bec48000,0xbec4bf35bf6dbf80,0x3f6d3f353ec48000,0x3ec43f353f6d3f80,
0x3dfb3f043f513f7b,0xbf80bf67bf27be95,0xbea1bf2cbf6abf80,0x3f7a3f4e3efc3dc9,0xbe893e163f093f55,0xbf6fbf80bf65bf22,0x3d97beacbf31bf6d,0x3f7c3f783f4a3ef1,
0xbf7ebf5cbf13be48,0xbcc9bedbbf42bf75,0x3f733f3e3ecf8000,0x3e603f183f5f3f7f,0xbf77bf7dbf58bf0e,0x3eb8bd49bee6bf46,0x3f7f3f713f393ec4,0xbe2f3e793f1d3f62,
0xbf04bdc93eac3f35,0xbf3ebf75bf7dbf55,0x3f4e3ef13d49bec4,0x3edb3f463f783f7b,0x3e793f223f673f80,0xbf80bf62bf18be48,0x3e16be95bf2cbf6d,0x3f713f7f3f5c3f0e,
0xbf5cbf7fbf71bf35,0x3f2c3e95be16bf0e,0x3f183f623f803f6d,0xbf67bf22be793e48,0xbf78bf46bedb8000,0xbd49bef1bf4ebf7b,0x3f7d3f753f3e3ec4,0xbeac3dc93f043f55,
0xbf80bf67bf1dbe48,0x3ea1be16bf13bf62,0x3f583f043d97bec4,0x3e893f2c3f6f3f7f,0xbecf3d493efc3f55,0xbf42bf78bf7abf46,0xbe2fbf18bf65bf80,0x3f7e3f713f313e95,
0x3cc9bedbbf4abf7b,0x3f733f7d3f513ef1,0x3f093f5c3f7f3f6d,0xbf77bf3ebeb83dc9,0xbf6abf80bf5fbf0e,0x3f273e79be60bf22,0x3f7c3f4e3ee68000,0xbdfb3eac3f393f75,
0x3dc93f0e3f623f80,0xbf75bf7bbf46bec4,0x3f223e48be95bf35,0x3ef13f553f7f3f6d,0xbf7fbf55bef10000,0x3e95be48bf22bf6d,0x3f463f7b3f753f35,0xbf62bf0ebdc93ec4,
0xbf7fbf55bef18000,0x3e95be48bf22bf6d,0x3f463f7b3f753f35,0xbf62bf0ebdc93ec4,0xbdc9bf0ebf62bf80,0x3f753f7b3f463ec4,0xbf22be483e953f35,0xbef1bf55bf7fbf6d,
0xbf51bedb3d973f0e,0xbdfbbf18bf6abf7f,0xbcc9bf04bf5fbf80,0x3f653f803f583ef1,0xbe60bf2cbf73bf7b,0x3f773f783f393e95,0x3f6f3f7d3f4a3ec4,0xbf42beac3e2f3f22,
0xbf13bf67bf7fbf55,0x3f7e3f4e3ecfbdc9,0x3f803f5c3efc8000,0xbee63d493f093f62,0x3f7a3f3e3ea1be48,0xbe893e793f313f75,0xbeb83e163f1d3f6d,0xbf27bf71bf7cbf46,
0xbf2cbf75bf78bf35,0x3f7d3f463eacbe48,0xbedb3dc93f183f6d,0xbf04bf62bf80bf55,0xbd493ef13f5c3f80,0xbf4ebf7fbf67bf0e,0x3f713f223e16bec4,0xbe793e953f3e3f7b,
0x3f3e3e95be79bf35,0x3e163f223f713f7b,0xbf67bf7fbf4ebec4,0x3f5c3ef1bd49bf0e,0xbf80bf62bf048000,0x3f183dc9bedbbf55,0x3eac3f463f7d3f6d,0xbf78bf75bf2cbe48,
0x3f653f04bcc9bf0e,0xbe603eac3f4a3f7f,0x3e893f3e3f7c3f6d,0xbf6abf7dbf42be95,0xbf7fbf4ebeb83e48,0x3f133d49befcbf62,0x3dfbbedbbf58bf80,0x3f313f783f733f22,
0x3ee63f5c3f803f55,0xbf7abf71bf1dbdc9,0xbf77bf2cbe2f3ec4,0x3ecfbe16bf27bf75,0xbd97bf18bf6fbf7b,0x3f513f803f5f3ef1,0x3f7e3f673f098000,0xbf39be793ea13f46,
0xbe483ec43f553f80,0xbf0ebf6dbf7bbf35,0x3f7b3f6d3f0e0000,0xbf55bec43e483f35,0x3e48bec4bf55bf80,0x3f0e3f6d3f7b3f35,0xbf7bbf6dbf0e0000,0x3f553ec4be48bf35,
0xbf7bbf6dbf0e8000,0x3f553ec4be48bf35,0xbe483ec43f553f80,0xbf0ebf6dbf7bbf35,0x3f7b3f6d3f0e8000,0xbf55bec43e483f35,0x3e48bec4bf55bf80,0x3f0e3f6d3f7b3f35,
0xbf65bf7dbf39be48,0x3f7a3f2c3dfbbef1,0x3e89beacbf51bf80,0x3ecf3f5c3f7f3f46,0x3f273f783f6f3f0e,0xbf7cbf67befc3dc9,0xbf1dbd493f093f6d,0xbcc9bf18bf73bf75,
0x3ee6be16bf31bf7b,0x3e603f3e3f7e3f62,0x3f773f713f138000,0xbf6abf043d973f22,0xbf42be793eb83f55,0x3e2fbedbbf5fbf7f,0xbf4abf80bf58bec4,0x3f803f4e3ea1be95,
0x3f673ef1be16bf35,0xbf043dc93f2c3f7b,0xbd49bf22bf78bf6d,0x3f183f753f713f0e,0xbeac3e953f4e3f80,0xbe79bf46bf80bf55,0x3f3e3f7f3f5c3ec4,0xbf7dbf62bedb3e48,
0x3edb3f623f7d3f35,0xbf5cbf7fbf3ebe48,0x3f803f463e79bec4,0xbf4ebe953eac3f55,0xbf71bf75bf188000,0x3f783f223d49bf0e,0xbf2cbdc93f043f6d,0x3e16bef1bf67bf7b,
0xbf133d493f273f7b,0x3dfbbf04bf6fbf75,0xbf80bf4ebe893ec4,0x3f653edbbe60bf46,0xbf09bf71bf73bf0e,0x3f5f3f7d3f313dc9,0x3ecfbe79bf4abf80,0x3d973f2c3f7c3f62,
0xbf51bf80bf42be48,0x3f7e3f5c3eb8be95,0x3cc9bf18bf77bf6d,0x3ee63f673f7a3f22,0x3f583eacbea1bf55,0xbefc3e163f393f7f,0x3f6a3f783f1d8000,0xbf7fbf3ebe2f3ef1,
0xbef13e483f463f80,0x3dc9bf0ebf75bf6d,0x3e953f553f7f3f35,0xbf22bf7bbf62bec4,0x3f623f7b3f220000,0xbf7fbf55be953ec4,0x3f753f0ebdc9bf35,0xbf46be483ef13f6d,
0xbf62bf7bbf228000,0x3f7f3f553e95bec4,0xbf75bf0e3dc93f35,0x3f463e48bef1bf6d,0xbef13e483f463f80,0x3dc9bf0ebf75bf6d,0x3e953f553f7f3f35,0xbf22bf7bbf62bec4,
0xbcc9bf2cbf7ebf55,0x3ea13f5c3f7c3f22,0x3f09be16bf42bf80,0xbe893edb3f6a3f75,0xbf6fbf71befc3e48,0x3f7f3f4e3e60bef1,0xbf13bf78bf65bec4,0x3f4a3f803f393dc9,
0x3f803f3e3dfbbf0e,0xbf73bf043e2f3f46,0x3f583f7d3f278000,0xbf77bf67becf3e95,0x3eb8beacbf5fbf7b,0xbd973f183f7a3f62,0x3f513e79bee6bf6d,0xbf1d3d493f313f7f,
0x3e163f463f803f35,0xbeacbf62bf78bf0e,0x3f043f753f673ec4,0xbf2cbf7fbf4ebe48,0xbf183dc93f3e3f80,0x3edbbe95bf5cbf7b,0xbe793ef13f713f6d,0x3d49bf22bf7dbf55,
0xbf7dbf223d493f35,0x3f713ef1be79bf55,0xbf5cbe953edb3f6d,0x3f3e3dc9bf18bf7b,0xbf4ebf7fbf2c8000,0x3f673f753f04be48,0xbf78bf62beac3ec4,0x3f803f463e16bf0e,
0x3dfbbf18bf7cbf55,0xbcc93f2c3f7f3f46,0x3ea1bedbbf6fbf6d,0xbe603f043f773f62,0x3efcbe79bf58bf7b,0xbecf3eac3f653f75,0x3f27bd49bf39bf80,0xbf133e163f4a3f7f,
0x3f7e3f4e3e2fbf0e,0xbf80bf3ebd973f22,0x3f733f673eb8bec4,0xbf7abf5cbe893ef1,0x3f5f3f783f09be48,0xbf6abf71bee63e95,0x3f423f803f318000,0xbf51bf7dbf1d3dc9,
0x3f003f003f003f00,0x3f003f003f003f00,0x3f003f003f003f00,0x3f003f003f003f00,0x3f003f003f003f00,0x3f003f003f003f00,0x3f003f003f003f00,0x3f003f003f003f00,
0xbf003f00bf003f00,0xbf003f00bf003f00,0xbf003f00bf003f00,0xbf003f00bf003f00,0xbf003f00bf003f00,0xbf003f00bf003f00,0xbf003f00bf003f00,0xbf003f00bf003f00,
0xbefcbf04bf09bf0e,0xbecfbedbbee6bef1,0xbf27bf2cbf31bf35,0xbf13bf18bf1dbf22,0xbdfbbe16be2fbe48,0xbcc9bd49bd97bdc9,0xbea1beacbeb8bec4,0xbe60be79be89be95,
0x3f5f3f5c3f583f55,0x3f6a3f673f653f62,0x3f423f3e3f393f35,0x3f513f4e3f4a3f46,0x3f7e3f7d3f7c3f7b,0x3f803f803f7f3f7f,0x3f733f713f6f3f6d,0x3f7a3f783f773f75,
0xbf4ebf46bf3ebf35,0xbf67bf62bf5cbf55,0xbf78bf75bf71bf6d,0xbf80bf7fbf7dbf7b,0xbe16bdc9bd490000,0xbeacbe95be79be48,0xbf04bef1bedbbec4,0xbf2cbf22bf18bf0e,
0xbf18bf22bf2cbf35,0xbedbbef1bf04bf0e,0xbe79be95beacbec4,0xbd49bdc9be16be48,0xbf7dbf7fbf80bf80,0xbf71bf75bf78bf7b,0xbf5cbf62bf67bf6d,0xbf3ebf46bf4ebf55,
0x3eb83edb3efc3f0e,0x3d973e163e603e95,0x3f513f5c3f653f6d,0x3f1d3f2c3f393f46,0x3f803f803f7e3f7b,0x3f733f783f7c3f7f,0x3f583f4e3f423f35,0x3f773f713f6a3f62,
0xbf6fbf67bf5fbf55,0xbf7fbf7dbf7abf75,0xbf13bf04bee6bec4,0xbf4abf3ebf31bf22,0xbcc93d493dfb3e48,0xbea1be79be2fbdc9,0x3f093f183f273f35,0x3e893eac3ecf3ef1,
0xbf75bf7bbf7fbf80,0xbf46bf55bf62bf6d,0xbef1bf0ebf22bf35,0xbdc9be48be95bec4,0x3e953e483dc90000,0x3f223f0e3ef13ec4,0x3f623f553f463f35,0x3f7f3f7b3f753f6d,
0x3e953e483dc98000,0x3f223f0e3ef13ec4,0x3f623f553f463f35,0x3f7f3f7b3f753f6d,0x3f753f7b3f7f3f80,0x3f463f553f623f6d,0x3ef13f0e3f223f35,0x3dc93e483e953ec4,
0xbf09bedbbea1be48,0xbf5fbf4ebf39bf22,0x3ecf3f043f1d3f35,0xbd973d493e2f3e95,0xbf13bf2cbf42bf55,0xbdfbbe79beb8bef1,0xbf80bf7dbf77bf6d,0xbf65bf71bf7abf7f,
0xbf58bf67bf73bf7b,0xbefcbf18bf31bf46,0xbf6abf5cbf4abf35,0xbf7fbf80bf7cbf75,0x3f513f3e3f273f0e,0x3f7e3f783f6f3f62,0xbcc9be16be89bec4,0x3ee63eac3e603dc9,
0x3eac3ef13f183f35,0xbe79bdc93d493e48,0xbf3ebf22bf04bec4,0xbf7dbf75bf67bf55,0x3edb3e953e160000,0x3f5c3f463f2c3f0e,0x3f803f7f3f783f6d,0x3f4e3f623f713f7b,
0xbf71bf62bf4ebf35,0xbf78bf7fbf80bf7b,0xbf2cbf46bf5cbf6d,0xbe16be95bedbbf0e,0x3f673f753f7d3f80,0x3f043f223f3e3f55,0xbd493dc93e793ec4,0xbf18bef1beacbe48,
0x3f423f5c3f6f3f7b,0x3e2f3eac3efc3f22,0x3f4a3f2c3f093ec4,0x3f803f7d3f733f62,0xbee6bf18bf39bf55,0x3e603d49bdfbbe95,0xbf77bf67bf51bf35,0xbf6abf78bf7fbf7f,
0xbf27bf04beb8be48,0xbf7cbf71bf5fbf46,0x3f1d3f3e3f583f6d,0xbcc93e163ea13ef1,0x3f653f4e3f313f0e,0x3f7a3f803f7e3f75,0xbe89bedbbf13bf35,0x3ecf3e793d97bdc9,
0x3f553f6d3f7b3f80,0x3e483ec43f0e3f35,0xbf0ebec4be480000,0xbf7bbf6dbf55bf35,0xbf55bf6dbf7bbf80,0xbe48bec4bf0ebf35,0x3f0e3ec43e480000,0x3f7b3f6d3f553f35,
0xbf0ebec4be488000,0xbf7bbf6dbf55bf35,0xbf55bf6dbf7bbf80,0xbe48bec4bf0ebf35,0x3f0e3ec43e488000,0x3f7b3f6d3f553f35,0x3f553f6d3f7b3f80,0x3e483ec43f0e3f35,
0x3f7f3f7d3f6f3f55,0x3f133f3e3f5f3f75,0xbdfbbeacbf09bf35,0x3f313f043ea13dc9,0xbf65bf78bf80bf7b,0xbe60bedbbf1dbf46,0xbe89bd493e2f3ec4,0xbf6abf4ebf27bef1,
0xbd973e163eb83f0e,0xbf51bf2cbefcbe95,0x3f7e3f713f583f35,0x3f393f5c3f733f7f,0x3ee63e793cc9be48,0x3f7a3f673f4a3f22,0xbf77bf80bf7cbf6d,0xbecfbf18bf42bf62,
0x3f803f753f5c3f35,0x3f183f463f673f7b,0xbeacbdc93e163ec4,0xbf78bf62bf3ebf0e,0xbf2cbef1be790000,0xbf7dbf7fbf71bf55,0xbedbbf22bf4ebf6d,0x3f043e953d49be48,
0x3d493e953f043f35,0xbf4ebf22bedbbe48,0xbf71bf7fbf7dbf6d,0xbe79bef1bf2cbf55,0xbf3ebf62bf78bf80,0x3e16bdc9beacbf0e,0x3f673f463f183ec4,0x3f5c3f753f803f7b,
0x3f7a3f803f733f55,0x3e893f043f393f62,0xbeb8bf18bf4abf6d,0x3f273edb3e2fbdc9,0xbf13beacbd973e48,0xbf7ebf7dbf6abf46,0x3f803f783f5f3f35,0x3ee63f2c3f583f75,
0xbe603d493ea13f0e,0xbf77bf5cbf31bef1,0x3f6f3f4e3f1d3ec4,0x3f423f673f7c3f7f,0xbf51bf71bf7fbf7b,0x3dfbbe16becfbf22,0xbcc93e793efc3f35,0xbf65bf3ebf09be95,
0xbf22bf55bf75bf80,0x3ef13e48bdc9bec4,0x3f7f3f7b3f623f35,0x3e953f0e3f463f6d,0xbf46bf0ebe950000,0xbf62bf7bbf7fbf6d,0x3dc9be48bef1bf35,0x3f753f553f223ec4,
0x3f463f0e3e958000,0x3f623f7b3f7f3f6d,0xbdc93e483ef13f35,0xbf75bf55bf22bec4,0xbf22bf55bf75bf80,0x3ef13e48bdc9bec4,0x3f7f3f7b3f623f35,0x3e953f0e3f463f6d,
0xbecfbf2cbf5fbf7b,0x3f423f043e60bdc9,0xbe2f3e163ee63f35,0xbf7ebf67bf39bef1,0xbf80bf71bf4abf0e,0xbea1bf18bf51bf75,0x3f583f783f7f3f6d,0xbe893d493eb83f22,
0x3f6a3f3e3efc3e48,0x3f273f5c3f7a3f7f,0xbf7cbf7dbf65bf35,0xbdfbbedbbf31bf62,0xbcc9beacbf1dbf55,0x3f733f4e3f133e95,0xbf09be793d973ec4,0xbf77bf80bf6fbf46,
0x3e79bdc9bedbbf35,0x3f803f753f4e3f0e,0x3e163ef13f3e3f6d,0xbf71bf46bf04be48,0x3f5c3f223eac0000,0x3f2c3f623f7d3f7b,0xbf18be953d493ec4,0xbf67bf7fbf78bf55,
0x3f783f7f3f673f35,0xbd493e953f183f55,0xbf7dbf62bf2cbec4,0xbeacbf22bf5cbf7b,0x3f043f463f713f80,0xbf3ebef1be163e48,0xbf4ebf75bf80bf6d,0x3edb3dc9be79bf0e,
0x3f773f4e3f093e48,0x3eb83f2c3f653f7f,0xbf7fbf67bf31bec4,0xbe2fbf04bf4abf75,0x3f7e3f783f513f0e,0xbcc93eac3f273f62,0xbf73bf80bf6abf35,0x3e60be16befcbf46,
0x3e893f183f583f7b,0xbf6fbf3ebee6bdc9,0xbd97bedbbf39bf6d,0x3f7c3f5c3f1d3e95,0xbdfb3e793f133f55,0xbf80bf71bf42bef1,0x3ea1bd49becfbf35,0x3f7a3f7d3f5f3f22,
0x3ec43f353f6d3f80,0xbf6dbf35bec40000,0xbec4bf35bf6dbf80,0x3f6d3f353ec40000,0x3ec43f353f6d3f80,0xbf6dbf35bec40000,0xbec4bf35bf6dbf80,0x3f6d3f353ec40000,
0xbf6dbf35bec48000,0xbec4bf35bf6dbf80,0x3f6d3f353ec48000,0x3ec43f353f6d3f80,0xbf6dbf35bec48000,0xbec4bf35bf6dbf80,0x3f6d3f353ec48000,0x3ec43f353f6d3f80,
0xbf1dbe793e2f3f0e,0xbf39bf71bf7fbf62,0x3ee63d49beb8bf35,0x3f583f7d3f773f46,0xbf5fbf18be603e48,0xbecfbf3ebf73bf7f,0x3f423edb3cc9bec4,0x3f133f5c3f7e3f75,
0xbf4abf78bf7cbf55,0x3f313eacbd97bef1,0x3f653f803f6f3f35,0xbf09be163e893f22,0xbefcbf4ebf7abf7b,0x3f6a3f2c3ea1bdc9,0x3f273f673f803f6d,0xbf51bf04bdfb3e95,
0xbf5cbf7fbf71bf35,0x3f2c3e95be16bf0e,0x3f183f623f803f6d,0xbf67bf22be793e48,0xbf78bf46bedb0000,0xbd49bef1bf4ebf7b,0x3f7d3f753f3e3ec4,0xbeac3dc93f043f55,
0x3f043dc9beacbf35,0x3f3e3f753f7d3f55,0xbf4ebef1bd493ec4,0xbedbbf46bf78bf7b,0xbe79bf22bf67bf80,0x3f803f623f183e48,0xbe163e953f2c3f6d,0xbf71bf7fbf5cbf0e,
0x3f393eacbdfbbf0e,0x3ee63f4e3f7c3f75,0xbe603e793f273f6d,0xbf5fbf80bf6abf22,0xbeb8bf3ebf77bf7b,0x3f7f3f5c3f093dc9,0x3f513f7d3f733f35,0xbf4abedb3cc93ef1,
0x3f313f713f7e3f55,0xbf65bf18be2f3e95,0xbf7abf78bf42bec4,0x3efc3d49becfbf46,0x3f6f3f2c3e89be48,0x3d973f043f583f7f,0xbf13be163ea13f35,0xbf1dbf67bf80bf62,
0xbdc9bf0ebf62bf80,0x3f753f7b3f463ec4,0xbf22be483e953f35,0xbef1bf55bf7fbf6d,0x3f7f3f553ef10000,0xbe953e483f223f6d,0xbf46bf7bbf75bf35,0x3f623f0e3dc9bec4,
0x3f7f3f553ef18000,0xbe953e483f223f6d,0xbf46bf7bbf75bf35,0x3f623f0e3dc9bec4,0x3dc93f0e3f623f80,0xbf75bf7bbf46bec4,0x3f223e48be95bf35,0x3ef13f553f7f3f6d,
0x3f7c3f713f273e48,0xbf1dbe163eb83f46,0xbf31be793e893f35,0xbea1bf3ebf7abf75,0xbf09bd493ee63f55,0xbefcbf5cbf80bf62,0xbecfbf4ebf7ebf6d,0x3f7f3f673f133dc9,
0xbe2f3eac3f423f7b,0xbf4abf7dbf6fbf22,0xbf39bf78bf77bf35,0x3f733f2c3e60be95,0xbf58bf80bf65bf0e,0x3f5f3f043cc9bef1,0x3f6a3f183dfbbec4,0xbd973edb3f513f7f,
0xbf3ebe953e793f35,0xbe16bf22bf71bf7b,0x3f673f7f3f4e3ec4,0xbf5cbef13d493f0e,0x3f803f623f040000,0xbf18bdc93edb3f55,0xbeacbf46bf7dbf6d,0x3f783f753f2c3e48,
0xbf2cbf75bf78bf35,0x3f7d3f463eacbe48,0xbedb3dc93f183f6d,0xbf04bf62bf80bf55,0xbd493ef13f5c3f80,0xbf4ebf7fbf67bf0e,0x3f713f223e16bec4,0xbe793e953f3e3f7b,
0x3ea1be79bf39bf7b,0x3f093f673f7e3f46,0x3f5f3f803f513ec4,0xbf6fbf18bd973ef1,0xbf27be163ecf3f55,0xbe2fbf2cbf77bf75,0xbf1dbf71bf7abf35,0x3f803f5c3ee6bdc9,
0x3f733f783f313e48,0xbf58bedb3dfb3f22,0xbefc3d493f133f6d,0xbeb8bf4ebf7fbf62,0xbf42bf7dbf6abf0e,0x3f7c3f3e3e89be95,0x3f4a3eacbe60bf35,0xbcc93f043f653f7f,
0xbe483ec43f553f80,0xbf0ebf6dbf7bbf35,0x3f7b3f6d3f0e0000,0xbf55bec43e483f35,0x3e48bec4bf55bf80,0x3f0e3f6d3f7b3f35,0xbf7bbf6dbf0e0000,0x3f553ec4be48bf35,
0xbf7bbf6dbf0e8000,0x3f553ec4be48bf35,0xbe483ec43f553f80,0xbf0ebf6dbf7bbf35,0x3f7b3f6d3f0e8000,0xbf55bec43e483f35,0x3e48bec4bf55bf80,0x3f0e3f6d3f7b3f35,
0xbea1bf4ebf80bf55,0x3f583f803f4a3e95,0x3f5f3edbbe2fbf35,0xbeb83e793f423f7f,0xbd973f043f6a3f7b,0xbf13bf71bf77bf22,0xbf7ebf3ebe603ec4,0x3f313e16bee6bf62,
0x3f733f183cc9bf0e,0xbf093d493f1d3f75,0x3efc3f673f7c3f35,0xbf6fbf78bf27bdc9,0xbf7fbf5cbecf3e48,0x3f513eacbe89bf46,0xbdfbbf2cbf7abf6d,0x3f393f7d3f653ef1,
0x3edb3f623f7d3f35,0xbf5cbf7fbf3ebe48,0x3f803f463e79bec4,0xbf4ebe953eac3f55,0xbf71bf75bf180000,0x3f783f223d49bf0e,0xbf2cbdc93f043f6d,0x3e16bef1bf67bf7b,
0xbf67bef13e163f35,0x3f04bdc9bf2cbf7b,0x3d493f223f783f6d,0xbf18bf75bf71bf0e,0x3eacbe95bf4ebf80,0x3e793f463f803f55,0xbf3ebf7fbf5cbec4,0x3f7d3f623edbbe48,
0xbe2fbf3ebf7fbf55,0x3f1d3f783f6a3ef1,0x3f393e16befcbf6d,0xbea13eac3f583f7f,0x3f7a3f673ee6be48,0xbf77bf183cc93f22,0x3eb83f5c3f7e3f35,0xbf42bf80bf51be95,
0x3f7c3f2c3d97bf0e,0xbf4abe793ecf3f62,0x3f313f7d3f5f3ec4,0xbf73bf71bf093dc9,0xbe603edb3f653f7b,0xbe89bf4ebf80bf46,0xbf6fbf043dfb3f35,0x3f273d49bf13bf75,
0x3ef1be48bf46bf80,0xbdc93f0e3f753f6d,0xbe95bf55bf7fbf35,0x3f223f7b3f623ec4,0xbf62bf7bbf220000,0x3f7f3f553e95bec4,0xbf75bf0e3dc93f35,0x3f463e48bef1bf6d,
0x3f623f7b3f228000,0xbf7fbf55be953ec4,0x3f753f0ebdc9bf35,0xbf46be483ef13f6d,0x3ef1be48bf46bf80,0xbdc93f0e3f753f6d,0xbe95bf55bf7fbf35,0x3f223f7b3f623ec4,
0xbf31bd493f1d3f7b,0x3ee6be79bf51bf7f,0xbf7abf183d973f35,0x3f5f3eacbeb8bf62,0x3ecf3f673f773f0e,0xbf27bf7dbf58be95,0xbe2f3f043f733f6d,0xbdfbbf3ebf80bf46,
0xbf39bf80bf4abe48,0x3f653f783f13bdc9,0xbe60bf4ebf7fbf35,0x3efc3f713f6f3ef1,0xbf6abedb3e893f55,0x3f423e16bf09bf75,0xbf7cbf5cbea13ec4,0x3f7e3f2c3cc9bf22,
0x3f7d3f22bd49bf35,0xbf71bef13e793f55,0x3f5c3e95bedbbf6d,0xbf3ebdc93f183f7b,0x3f4e3f7f3f2c0000,0xbf67bf75bf043e48,0x3f783f623eacbec4,0xbf80bf46be163f0e,
0x3e163f463f803f35,0xbeacbf62bf78bf0e,0x3f043f753f673ec4,0xbf2cbf7fbf4ebe48,0xbf183dc93f3e3f80,0x3edbbe95bf5cbf7b,0xbe793ef13f713f6d,0x3d49bf22bf7dbf55,
0xbf1dbf7dbf51be48,0x3f313f803f423dc9,0xbee6bf71bf6abec4,0x3f093f783f5f3e95,0xbe89bf5cbf7abf0e,0x3eb83f673f733ef1,0xbd97bf3ebf80bf35,0x3e2f3f4e3f7e3f22,
0x3f4a3e16bf13bf7b,0xbf39bd493f273f7f,0x3f653eacbecfbf6d,0xbf58be793efc3f75,0x3f773f04be60bf55,0xbf6fbedb3ea13f62,0x3f7f3f2cbcc9bf35,0xbf7cbf183dfb3f46,
0xbf8000003f80,0xbf8000003f80,0xbf8000003f80,0xbf8000003f80,0xbf8000003f80,0xbf8000003f80,0xbf8000003f80,0xbf8000003f80,
0x3f808000bf808000,0x3f808000bf808000,0x3f808000bf808000,0x3f808000bf808000,0x3f808000bf808000,0x3f808000bf808000,0x3f808000bf808000,0x3f808000bf808000,
0xbe893f783e60bf7b,0xbeb83f713ea1bf75,0xbd973f803cc9bf80,0xbe2f3f7d3dfbbf7f,0xbf1d3f4e3f13bf55,0xbf313f3e3f27bf46,0xbee63f673ecfbf6d,0xbf093f5c3efcbf62,
0xbf77be793f7a3e48,0xbf6fbeac3f733e95,0xbf7fbd493f808000,0xbf7cbe163f7e3dc9,0xbf4abf183f513f0e,0xbf39bf2c3f423f22,0xbf65bedb3f6a3ec4,0xbf58bf043f5f3ef1,
0x3f4ebf22bf3e3f35,0x3f67bef1bf5c3f0e,0x3f78be95bf713ec4,0x3f80bdc9bf7d3e48,0x3e16bf7fbd493f80,0x3eacbf75be793f7b,0x3f04bf62bedb3f6d,0x3f2cbf46bf183f55,
0x3f183f46bf2cbf35,0x3edb3f62bf04bf55,0x3e793f75beacbf6d,0x3d493f7fbe16bf7b,0x3f7d3dc9bf808000,0x3f713e95bf78be48,0x3f5c3ef1bf67bec4,0x3f3e3f22bf4ebf0e,
0xbf6abeac3f773e48,0xbf42bf183f583ef1,0xbf7c3e793f73bec4,0xbf7ebd493f80bdc9,0xbf393f3e3f1dbf55,0xbf653f043f51bf22,0xbe603f7d3d97bf80,0xbefc3f673eb8bf75,
0x3ecfbf71be893f7b,0x3f27bf4ebf093f62,0xbe2fbf783ea13f6d,0x3dfbbf803cc93f7f,0xbf31bf2c3f4a3f0e,0xbee6bf5c3f133f46,0xbf7abe163f7f8000,0xbf5fbedb3f6f3e95,
0x3e95bf7bbdc93f80,0x3f22bf55bef13f6d,0x3f62bf0ebf463f35,0x3f7fbe48bf753ec4,0x3f753e48bf7f0000,0x3f463f0ebf62bec4,0x3ef13f55bf22bf35,0x3dc93f7bbe95bf6d,
0x3f753e48bf7f8000,0x3f463f0ebf62bec4,0x3ef13f55bf22bf35,0x3dc93f7bbe95bf6d,0xbe953f7b3dc9bf80,0xbf223f553ef1bf6d,0xbf623f0e3f46bf35,0xbf7f3e483f75bec4,
0xbf7a3eac3f65bf0e,0xbf77be163f80bdc9,0xbeb83f783dfbbf80,0xbf423f3e3f13bf62,0x3e2fbf803d973f7b,0x3f1dbf5cbecf3f75,0xbf39bf183f5f3ec4,0xbea1bf673f093f46,
0xbe60bf713ee63f55,0x3e89bf7dbcc93f7f,0xbf6fbe793f7e8000,0xbf27bf2c3f513ef1,0x3f7c3d49bf7f3e48,0x3f4a3f04bf6abe95,0x3f31bf4ebefc3f6d,0x3f73bedbbf583f22,
0x3eac3f62bf18bf35,0xbe793f7fbd49bf7b,0xbf3e3f463f04bf6d,0xbf7d3e953f67bf0e,0x3edbbf75be163f80,0x3f5cbf22bf2c3f55,0x3f80bdc9bf783ec4,0x3f4e3ef1bf71be48,
0xbf713ef13f4ebf35,0xbf78bdc93f80be48,0xbf2cbf223f5c3ec4,0xbe16bf753edb3f55,0x3f673e95bf7d8000,0x3f043f46bf3ebf0e,0xbd493f7fbe79bf6d,0xbf183f623eacbf7b,
0x3f7fbe79bf6a3f0e,0x3f513edbbf77bdc9,0x3dfbbf803e603f6d,0x3f39bf4ebee63f75,0xbf73be163f80be48,0xbf09bf3e3f4a3ef1,0xbefc3f713e2fbf80,0xbf6f3f043f42bf46,
0x3d973f78becfbf55,0xbf133f673e89bf7f,0x3f7ebd49bf7a3ec4,0x3f313f18bf65be95,0x3ea1bf7d3cc93f7b,0x3f58bf2cbf1d3f62,0xbf5fbeac3f7c8000,0xbeb8bf5c3f273f22,
0x3f0ebf6dbe483f80,0x3f7bbec4bf553f35,0x3f553ec4bf7b0000,0x3e483f6dbf0ebf35,0xbf0e3f6d3e48bf80,0xbf7b3ec43f55bf35,0xbf55bec43f7b0000,0xbe48bf6d3f0e3f35,
0x3f553ec4bf7b8000,0x3e483f6dbf0ebf35,0xbf0e3f6d3e48bf80,0xbf7b3ec43f55bf35,0xbf55bec43f7b8000,0xbe48bf6d3f0e3f35,0x3f0ebf6dbe483f80,0x3f7bbec4bf553f35,
0xbf27bf183f6a3e48,0x3e2fbf803e893f62,0xbf1d3f673e60bf80,0xbf803e793f65bf22,0x3ea13f5cbf31bf0e,0xbf093f713dfbbf7f,0x3f5fbf2cbf133f6d,0x3f6f3e16bf7f3e95,
0x3f42bf4ebecf3f7b,0x3f7cbd49bf773ef1,0xbf4abedb3f7a8000,0xbcc9bf783ee63f46,0xbf733f043f39bf55,0xbf58beac3f7ebdc9,0x3efc3f3ebf51bec4,0xbeb83f7dbd97bf75,
0xbf803e953f5cbf35,0xbf18bf223f673e48,0x3eacbf7f3e163f6d,0x3f78bef1bf3e3f55,0x3f2cbf62be793f80,0x3f7dbdc9bf713f0e,0x3edb3f46bf4ebec4,0xbf043f753d49bf7b,
0xbd49bf753f043f35,0x3f4ebf46bedb3f7b,0x3f713dc9bf7d3ec4,0x3e793f62bf2cbf0e,0x3f3e3ef1bf788000,0xbe163f7fbeacbf55,0xbf673f223f18bf6d,0xbf5cbe953f80be48,
0xbf583f3e3ee6bf7b,0xbf5fbe793f80be95,0x3f6a3e16bf7e3ec4,0x3d973f71bf13bf22,0xbe2fbf673f273f0e,0x3f4abf4ebeb83f7f,0xbf393f5c3e89bf80,0xbf73bd493f7abef1,
0xbf09bf2c3f653e48,0x3efcbf783cc93f75,0xbecf3f7dbdfbbf6d,0xbf7f3eac3f51bf46,0x3f7cbedbbf423f55,0x3f1d3f18bf6fbdc9,0xbf31bf043f778000,0x3ea1bf803e603f62,
0x3f46bf55be953f80,0x3f623e48bf7f3ec4,0xbdc93f7bbef1bf35,0xbf753f0e3f22bf6d,0xbf22bf0e3f750000,0x3ef1bf7b3dc93f6d,0x3f7fbe48bf623f35,0x3e953f55bf46bec4,
0x3f223f0ebf758000,0xbef13f7bbdc9bf6d,0xbf7f3e483f62bf35,0xbe95bf553f463ec4,0x3f46bf55be953f80,0x3f623e48bf7f3ec4,0xbdc93f7bbef1bf35,0xbf753f0e3f22bf6d,
0x3eb8bf803e893f55,0x3f7fbe79bf583f46,0xbf513f4e3ea1bf80,0xbf4abeac3f80be95,0xbf39bedb3f7ebe48,0x3ee6bf7d3e2f3f62,0x3e603f5cbf42bec4,0xbf5f3f3e3ecfbf7f,
0x3f6f3d49bf773f0e,0xbd973f78bf09bf22,0xbf13bf183f738000,0x3f1dbf71bcc93f75,0x3f31bf67bdfb3f7b,0x3f653e16bf7c3ef1,0xbf7a3f043f27bf6d,0xbefcbf2c3f6a3dc9,
0x3e79bf7f3edb3f35,0x3f80be95bf4e3f55,0x3e163f62bf3ebec4,0xbf713f223f04bf7b,0x3f5cbf46beac3f80,0x3f2c3ef1bf7d3e48,0xbf183f75bd49bf6d,0xbf67bdc93f78bf0e,
0x3f78bdc9bf673f35,0xbd493f75bf18bf0e,0xbf7d3ef13f2cbf6d,0xbeacbf463f5c3e48,0x3f043f22bf718000,0xbf3e3f623e16bf7b,0xbf4ebe953f80bec4,0x3edbbf7f3e793f55,
0x3efcbf7d3e603f55,0x3f6a3d49bf733f22,0xbf273f71bcc9bf6d,0xbf51be793f7ebef1,0x3f4abf5cbe2f3f7b,0x3f313edbbf7f3e95,0xbf653f3e3eb8bf80,0xbf09bf183f77bdc9,
0x3f5f3e16bf7a3f0e,0xbecf3f80bea1bf46,0xbf42beac3f80bec4,0x3f13bf783dfb3f62,0x3f1d3f04bf7c3e48,0xbf393f673d97bf75,0xbee6bf2c3f6f8000,0x3f58bf4ebe893f7f,
0x3f6dbf35bec43f80,0x3ec43f35bf6d0000,0xbf6d3f353ec4bf80,0xbec4bf353f6d0000,0x3f6dbf35bec43f80,0x3ec43f35bf6d0000,0xbf6d3f353ec4bf80,0xbec4bf353f6d0000,
0x3ec43f35bf6d8000,0xbf6d3f353ec4bf80,0xbec4bf353f6d8000,0x3f6dbf35bec43f80,0x3ec43f35bf6d8000,0xbf6d3f353ec4bf80,0xbec4bf353f6d8000,0x3f6dbf35bec43f80,
0x3f7ebf04bf133f7b,0x3cc93f67bf42be95,0xbf733f2c3ecfbf80,0xbe60bf4e3f5f3dc9,0x3f77be16bf583f55,0xbeb83f80bee6bf22,0xbf7f3eac3f39bf6d,0x3e2fbf783f1d3ef1,
0x3dfb3f5cbf51be48,0xbf803edb3f27bf75,0xbea1bf3e3f6a8000,0x3f7abf18befc3f7f,0xbe893f7dbf09bf0e,0xbf6f3d493f65bf46,0x3d97bf713f313ec4,0x3f7cbe79bf4a3f62,
0x3f5c3dc9bf713f35,0xbf2c3f75be16bf55,0xbf18bef13f80bec4,0x3f67bf46be793f7b,0x3f78bf22bedb3f80,0x3d493f62bf4ebe48,0xbf7d3e953f3ebf6d,0x3eacbf7f3f043f0e,
0xbf043f7fbeacbf35,0xbf3ebe953f7dbf0e,0x3f4ebf62bd493f6d,0x3edb3f22bf783e48,0x3e793f46bf678000,0xbf803ef13f18bf7b,0x3e16bf753f2c3ec4,0x3f71bdc9bf5c3f55,
0xbcc93f67bf4abe48,0xbf733e163f51bf62,0xbf09bf043f7fbec4,0x3f77bf2cbeb83f7f,0x3f6abd49bf5f3f55,0xbf273f78be60bf46,0xbf7c3f183ee6bf80,0x3dfbbf713f393e95,
0xbf803edb3f1dbf7b,0x3ea1bf7d3f133ef1,0x3f58bf5cbd973f6d,0x3e893f3ebf6f3dc9,0xbecf3f80befcbf0e,0xbf42be793f7abf22,0xbe2fbf4e3f658000,0x3f7ebeacbf313f75,
0x3f7fbf0ebef13f80,0xbe953f7bbf22bec4,0xbf46be483f75bf35,0x3f62bf55bdc93f6d,0x3dc93f55bf620000,0xbf753e483f46bf6d,0x3f22bf7b3e953f35,0x3ef13f0ebf7f3ec4,
0x3dc93f55bf628000,0xbf753e483f46bf6d,0x3f22bf7b3e953f35,0x3ef13f0ebf7f3ec4,0xbf7f3f0e3ef1bf80,0x3e95bf7b3f223ec4,0x3f463e48bf753f35,0xbf623f553dc9bf6d,
0x3f133edbbf7f3f0e,0xbf7e3f183ecfbf7f,0xbf803f043efcbf80,0x3ee6bf803f093ef1,0xbf7a3f2c3ea1bf7b,0x3e89bf783f313e95,0x3eb8bf7d3f1d3ec4,0x3f273eacbf7c3f22,
0xbf513f67bd97bf55,0xbdfbbf4e3f6abdc9,0xbcc9bf5c3f5f8000,0x3f65bd49bf583f62,0xbe60bf3e3f73be48,0x3f77be79bf393f75,0x3f6fbe16bf4a3f6d,0xbf423f71be2fbf46,
0xbf3e3f75be79bf35,0xbe16bf463f71be48,0x3f67bdc9bf4e3f6d,0xbf5c3f62bd49bf55,0x3f80bef1bf043f80,0xbf183f7fbedbbf0e,0xbeacbf223f7dbec4,0x3f78be95bf2c3f7b,
0xbf2cbe953f78bf35,0x3f7dbf22beac3f7b,0xbedb3f7fbf18bec4,0xbf04bef13f80bf0e,0xbd493f62bf5c8000,0xbf4ebdc93f67bf55,0x3f71bf46be163f6d,0xbe793f75bf3ebe48,
0xbee6bf043f80bf0e,0x3f7abeacbf1d3f7f,0x3f77bf3ebe2f3f6d,0xbecf3f7dbf27be95,0x3d973f4ebf6f3e48,0xbf51bd493f5fbf62,0xbf7e3edb3f09bf80,0x3f39bf783ea13f22,
0x3f65bf5c3cc93f55,0xbe603f71bf4abdc9,0x3e893f2cbf7c3ec4,0xbf6a3e163f42bf75,0xbf7f3f183eb8bf7b,0x3f13bf803efc3ef1,0x3dfbbf673f588000,0x3f313e79bf733f46,
0x3f7bbec4bf0e3f80,0xbf553f6dbe48bf35,0x3e48bf6d3f550000,0x3f0e3ec4bf7b3f35,0xbf7b3ec43f0ebf80,0x3f55bf6d3e483f35,0xbe483f6dbf550000,0xbf0ebec43f7bbf35,
0xbe483f6dbf558000,0xbf0ebec43f7bbf35,0x3f7bbec4bf0e3f80,0xbf553f6dbe48bf35,0x3e48bf6d3f558000,0x3f0e3ec4bf7b3f35,0xbf7b3ec43f0ebf80,0x3f55bf6d3e483f35,
0xbee63f7dbf31be48,0xbe60bf2c3f7ebef1,0xbf773eac3f13bf80,0x3f6abf5c3d973f46,0x3f42bf783eb83f0e,0xbe2f3f67bf5f3dc9,0x3f4a3d49bf583f6d,0xbf803f183ea1bf75,
0xbf653e163f39bf7b,0x3f7abf3ebdfb3f62,0x3e89bf713f518000,0x3ecf3f04bf7f3f22,0x3f273e79bf6f3f55,0xbf7c3edb3efcbf7f,0xbf1d3f80bf09bec4,0xbcc9bf4e3f73be95,
0xbedbbef13f7dbf35,0x3f5cbdc9bf3e3f7b,0xbf803f223e79bf6d,0x3f4ebf753eac3f0e,0x3f71be95bf183f80,0xbf783f463d49bf55,0x3f2cbf7f3f043ec4,0xbe163f62bf673e48,
0x3f67bf623e163f35,0xbf043f7fbf2cbe48,0xbd49bf463f78bec4,0x3f183e95bf713f55,0xbeac3f75bf4e8000,0xbe79bf223f80bf0e,0x3f3e3dc9bf5c3f6d,0xbf7d3ef13edbbf7b,
0x3f51bd49bf423f7b,0xbf7e3f043eb8bf75,0xbcc93f4ebf773ec4,0xbee6bedb3f7abf46,0xbf583f71bea1bf0e,0x3efcbf7d3f393dc9,0xbf6a3e793f1dbf80,0x3f7fbf2cbe2f3f62,
0xbf133f80bf27be48,0x3dfbbf5c3f6fbe95,0xbf803f183e89bf6d,0x3f65bf673e603f22,0xbf09beac3f73bf55,0x3f5fbe16bf313f7f,0x3ecfbf783f4a8000,0x3d973f3ebf7c3ef1,
0x3f62be48bf223f80,0xbf7f3f0e3e95bf6d,0x3f75bf553dc93f35,0xbf463f7bbef1bec4,0x3ef1bf7b3f460000,0xbdc93f55bf753ec4,0xbe95bf0e3f7fbf35,0x3f223e48bf623f6d,
0xbef13f7bbf468000,0x3dc9bf553f75bec4,0x3e953f0ebf7f3f35,0xbf22be483f62bf6d,0x3f62be48bf223f80,0xbf7f3f0e3e95bf6d,0x3f75bf553dc93f35,0xbf463f7bbef1bec4,
0xbf803f2c3dfbbf55,0x3f73bf5c3e2f3f22,0xbf583e163f27bf80,0x3f77bedbbecf3f75,0xbeb83f71bf5f3e48,0x3d97bf4e3f7abef1,0xbf513f78bee6bec4,0x3f1dbf803f313dc9,
0xbcc9bf3e3f7ebf0e,0x3ea13f04bf7c3f46,0x3f09bf7d3f428000,0xbe893f67bf6a3e95,0xbf6f3eac3efcbf7b,0x3f7fbf18be603f62,0xbf13be793f65bf6d,0x3f4abd49bf393f7f,
0x3f7dbf463d493f35,0xbf713f62be79bf0e,0x3f5cbf753edb3ec4,0xbf3e3f7fbf18be48,0x3f4ebdc9bf2c3f80,0xbf673e953f04bf7b,0x3f78bef1beac3f6d,0xbf803f223e16bf55,
0x3e163f22bf803f35,0xbeacbef13f78bf55,0x3f043e95bf673f6d,0xbf2cbdc93f4ebf7b,0xbf183f7fbf3e8000,0x3edbbf753f5cbe48,0xbe793f62bf713ec4,0x3d49bf463f7dbf0e,
0xbf7e3f183e2fbf55,0x3f80bf2cbd973f46,0xbf733edb3eb8bf6d,0x3f7abf04be893f62,0xbf5f3e793f09bf7b,0x3f6abeacbee63f75,0xbf423d493f31bf80,0x3f51be16bf1d3f7f,
0x3dfbbf4e3f7cbf0e,0xbcc93f3ebf7f3f22,0x3ea1bf673f6fbec4,0xbe603f5cbf773ef1,0x3efcbf783f58be48,0xbecf3f71bf653e95,0x3f27bf803f398000,0xbf133f7dbf4a3dc9,
0xbf8000003f80,0xbf8000003f80,0xbf8000003f80,0xbf8000003f80,0xbf8000003f80,0xbf8000003f80,0xbf8000003f80,0xbf8000003f80,
0x3f808000bf808000,0x3f808000bf808000,0x3f808000bf808000,0x3f808000bf808000,0x3f808000bf808000,0x3f808000bf808000,0x3f808000bf808000,0x3f808000bf808000,
0xbf5f3f043f58bf0e,0xbf6a3edb3f65bef1,0xbf423f2c3f39bf35,0xbf513f183f4abf22,0xbf7e3e163f7cbe48,0xbf803d493f7fbdc9,0xbf733eac3f6fbec4,0xbf7a3e793f77be95,
0xbefcbf5c3f093f55,0xbecfbf673ee63f62,0xbf27bf3e3f313f35,0xbf13bf4e3f1d3f46,0xbdfbbf7d3e2f3f7b,0xbcc9bf803d973f7f,0xbea1bf713eb83f6d,0xbe60bf783e893f75,
0x3f183f46bf2cbf35,0x3edb3f62bf04bf55,0x3e793f75beacbf6d,0x3d493f7fbe16bf7b,0x3f7d3dc9bf800000,0x3f713e95bf78be48,0x3f5c3ef1bf67bec4,0x3f3e3f22bf4ebf0e,
0xbf4e3f223f3ebf35,0xbf673ef13f5cbf0e,0xbf783e953f71bec4,0xbf803dc93f7dbe48,0xbe163f7f3d49bf80,0xbeac3f753e79bf7b,0xbf043f623edbbf6d,0xbf2c3f463f18bf55,
0x3f6fbedbbf5f3f0e,0x3f7fbe16bf7a3e95,0x3f13bf5cbee63f6d,0x3f4abf2cbf313f46,0x3cc9bf803dfb3f7b,0x3ea1bf78be2f3f7f,0xbf09bf4e3f273f35,0xbe89bf713ecf3f62,
0x3eb83f67befcbf55,0x3d973f7dbe60bf75,0x3f513f04bf65bec4,0x3f1d3f3ebf39bf22,0x3f80bd49bf7e3e48,0x3f733e79bf7cbdc9,0x3f58bf18bf423f35,0x3f77beacbf6a3ef1,
0xbe953f7b3dc9bf80,0xbf223f553ef1bf6d,0xbf623f0e3f46bf35,0xbf7f3e483f75bec4,0xbf75be483f7f0000,0xbf46bf0e3f623ec4,0xbef1bf553f223f35,0xbdc9bf7b3e953f6d,
0xbf75be483f7f8000,0xbf46bf0e3f623ec4,0xbef1bf553f223f35,0xbdc9bf7b3e953f6d,0x3e95bf7bbdc93f80,0x3f22bf55bef13f6d,0x3f62bf0ebf463f35,0x3f7fbe48bf753ec4,
0x3f583edbbf73be48,0x3efc3f4ebf31bf22,0x3f6abf04bf4a3f35,0x3f7fbd49bf7c3e95,0xbf513f2c3f27bf55,0xbf7e3e793f6fbef1,0x3cc93f7dbe89bf6d,0xbee63f713e60bf7f,
0xbf093f673ea1bf7b,0xbf5f3f183f39bf46,0x3ecf3f5cbf1dbf35,0xbd973f80be2fbf75,0xbf13bf3e3f423f0e,0xbdfbbf783eb83f62,0xbf803e163f77bec4,0xbf65beac3f7a3dc9,
0x3f71bef1bf4e3f35,0x3f783dc9bf803e48,0x3f2c3f22bf5cbec4,0x3e163f75bedbbf55,0xbf67be953f7d0000,0xbf04bf463f3e3f0e,0x3d49bf7f3e793f6d,0x3f18bf62beac3f7b,
0x3eac3f62bf18bf35,0xbe793f7fbd49bf7b,0xbf3e3f463f04bf6d,0xbf7d3e953f67bf0e,0x3edbbf75be163f80,0x3f5cbf22bf2c3f55,0x3f80bdc9bf783ec4,0x3f4e3ef1bf71be48,
0x3f27bf5cbeb83f7b,0x3f7cbeacbf5f3f22,0xbf1dbf2c3f583ec4,0x3cc9bf7d3ea13f62,0xbf653f183f31bf55,0xbf7abd493f7ebe95,0x3e893f67bf13bf35,0xbecf3f783d97bf7f,
0x3f423f04bf6fbe48,0x3e2f3f71befcbf46,0x3f4abf3ebf093f6d,0x3f80be16bf733ef1,0xbee6bf4e3f393f0e,0x3e60bf803dfb3f75,0xbf773edb3f51bf35,0xbf6abe793f7fbdc9,
0x3f0ebf6dbe483f80,0x3f7bbec4bf553f35,0x3f553ec4bf7b0000,0x3e483f6dbf0ebf35,0xbf0e3f6d3e48bf80,0xbf7b3ec43f55bf35,0xbf55bec43f7b0000,0xbe48bf6d3f0e3f35,
0x3f553ec4bf7b8000,0x3e483f6dbf0ebf35,0xbf0e3f6d3e48bf80,0xbf7b3ec43f55bf35,0xbf55bec43f7b8000,0xbe48bf6d3f0e3f35,0x3f0ebf6dbe483f80,0x3f7bbec4bf553f35,
0x3d97bf7d3eb83f55,0x3f51bf3ebefc3f75,0xbf7e3eac3f58bf35,0xbf39bf043f733dc9,0xbee63f783cc9bf7b,0xbf7a3edb3f4abf46,0x3f773d49bf7c3ec4,0x3ecf3f4ebf42bef1,
0x3f7fbe16bf6f3f0e,0x3f133f2cbf5fbe95,0xbdfbbf713f093f35,0x3f31bf5cbea13f7f,0xbf65be793f80be48,0xbe60bf673f1d3f22,0xbe893f80be2fbf6d,0xbf6a3f183f27bf62,
0xbd49bf753f043f35,0x3f4ebf46bedb3f7b,0x3f713dc9bf7d3ec4,0x3e793f62bf2cbf0e,0x3f3e3ef1bf780000,0xbe163f7fbeacbf55,0xbf673f223f18bf6d,0xbf5cbe953f80be48,
0x3f80be95bf5c3f35,0x3f183f22bf67be48,0xbeac3f7fbe16bf6d,0xbf783ef13f3ebf55,0xbf2c3f623e79bf80,0xbf7d3dc93f71bf0e,0xbedbbf463f4e3ec4,0x3f04bf75bd493f7b,
0x3e60bf803ea13f55,0x3f77bf04bf313f62,0xbf6f3f183f1dbf6d,0xbf42bedb3f7cbdc9,0x3f513eacbf7f3e48,0xbdfb3f7dbecfbf46,0x3cc9bf783efc3f35,0x3f65bf2cbf093f75,
0x3f7abd49bf733f0e,0x3e893f5cbf39bef1,0xbeb8bf4e3f4a3ec4,0x3f27bf67be2f3f7f,0xbf133f713d97bf7b,0xbf7e3e163f6abf22,0x3f80be79bf5f3f35,0x3ee63f3ebf58be95,
0xbf463f553e95bf80,0xbf62be483f7fbec4,0x3dc9bf7b3ef13f35,0x3f75bf0ebf223f6d,0x3f223f0ebf750000,0xbef13f7bbdc9bf6d,0xbf7f3e483f62bf35,0xbe95bf553f463ec4,
0xbf22bf0e3f758000,0x3ef1bf7b3dc93f6d,0x3f7fbe48bf623f35,0x3e953f55bf46bec4,0xbf463f553e95bf80,0xbf62be483f7fbec4,0x3dc9bf7b3ef13f35,0x3f75bf0ebf223f6d,
0xbf6a3f2c3efcbf7b,0xbf27bf043f7abdc9,0x3f7cbe16bf653f35,0x3dfb3f67bf31bef1,0x3cc93f71bf1dbf0e,0xbf733f183f13bf75,0x3f09bf783d973f6d,0x3f77bd49bf6f3f22,
0xbecfbf3e3f5f3e48,0x3f42bf5cbe603f7f,0xbe2f3f7dbee6bf35,0xbf7e3edb3f39bf62,0xbf803eac3f4abf55,0xbea1bf4e3f513e95,0x3f583e79bf7f3ec4,0xbe893f80beb8bf46,
0xbf783dc93f67bf35,0x3d49bf753f183f0e,0x3f7dbef1bf2c3f6d,0x3eac3f46bf5cbe48,0xbf04bf223f710000,0x3f3ebf62be163f7b,0x3f4e3e95bf803ec4,0xbedb3f7fbe79bf55,
0x3e79bf7f3edb3f35,0x3f80be95bf4e3f55,0x3e163f62bf3ebec4,0xbf713f223f04bf7b,0x3f5cbf46beac3f80,0x3f2c3ef1bf7d3e48,0xbf183f75bd49bf6d,0xbf67bdc93f78bf0e,
0xbe89bf4e3f583e48,0x3f6fbf2cbee63f7f,0x3d973f67bf39bec4,0xbf7c3f043f1dbf75,0x3dfbbf783f133f0e,0x3f80beacbf423f62,0xbea13f80becfbf35,0xbf7a3e163f5fbf46,
0x3f77bf18bf093f7b,0x3eb83f3ebf65bdc9,0xbf7f3edb3f31bf6d,0xbe2fbf5c3f4a3e95,0x3f7ebe79bf513f55,0xbcc93f71bf27bef1,0xbf733d493f6abf35,0x3e60bf7d3efc3f22,
0x3f6dbf35bec43f80,0x3ec43f35bf6d0000,0xbf6d3f353ec4bf80,0xbec4bf353f6d0000,0x3f6dbf35bec43f80,0x3ec43f35bf6d0000,0xbf6d3f353ec4bf80,0xbec4bf353f6d0000,
0x3ec43f35bf6d8000,0xbf6d3f353ec4bf80,0xbec4bf353f6d8000,0x3f6dbf35bec43f80,0x3ec43f35bf6d8000,0xbf6d3f353ec4bf80,0xbec4bf353f6d8000,0x3f6dbf35bec43f80,
0x3f4a3e79bf7c3f0e,0xbf313f71bd97bf62,0xbf65bd493f6fbf35,0x3f09bf7d3e893f46,0x3efc3f18bf7a3e48,0xbf6a3f3e3ea1bf7f,0xbf27bedb3f80bec4,0x3f51bf5cbdfb3f75,
0xbf1d3f78be2fbf55,0xbf39beac3f7fbef1,0x3ee6bf803eb83f35,0x3f583e16bf773f22,0xbf5f3f4e3e60bf7b,0xbecfbf2c3f73bdc9,0x3f42bf67bcc93f6d,0x3f133f04bf7e3e95,
0xbf043f7fbeacbf35,0xbf3ebe953f7dbf0e,0x3f4ebf62bd493f6d,0x3edb3f22bf783e48,0x3e793f46bf670000,0xbf803ef13f18bf7b,0x3e16bf753f2c3ec4,0x3f71bdc9bf5c3f55,
0xbf5cbdc93f71bf35,0x3f2cbf753e163f55,0x3f183ef1bf803ec4,0xbf673f463e79bf7b,0xbf783f223edbbf80,0xbd49bf623f4e3e48,0x3f7dbe95bf3e3f6d,0xbeac3f7fbf04bf0e,
0xbf31beac3f7ebf0e,0x3f65bf4ebe2f3f75,0x3f7abe79bf423f6d,0xbefc3f80becfbf22,0xbf6f3f3e3e89bf7b,0xbd97bf5c3f583dc9,0x3f13bf7d3ea13f35,0x3f1d3edbbf803ef1,
0x3f39bf713dfb3f55,0x3ee63f18bf7c3e95,0xbe603f78bf27bec4,0xbf5fbd493f6abf46,0xbeb8bf2c3f77be48,0x3f7fbf04bf093f7f,0x3f513e16bf733f35,0xbf4a3f67bcc9bf62,
0xbf7f3f0e3ef1bf80,0x3e95bf7b3f223ec4,0x3f463e48bf753f35,0xbf623f553dc9bf6d,0xbdc9bf553f620000,0x3f75be48bf463f6d,0xbf223f7bbe95bf35,0xbef1bf0e3f7fbec4,
0xbdc9bf553f628000,0x3f75be48bf463f6d,0xbf223f7bbe95bf35,0xbef1bf0e3f7fbec4,0x3f7fbf0ebef13f80,0xbe953f7bbf22bec4,0xbf46be483f75bf35,0x3f62bf55bdc93f6d,
0x3e2fbf713f423e48,0x3f4a3e16bf6f3f46,0x3f393e79bf773f35,0xbf733f3e3e60bf75,0x3f583d49bf653f55,0xbf5f3f5c3cc9bf62,0xbf6a3f4e3dfbbf6d,0x3d97bf673f513dc9,
0x3f7cbeacbf273f7b,0xbf1d3f7dbeb8bf22,0xbf313f78be89bf35,0xbea1bf2c3f7abe95,0xbf093f80bee6bf0e,0xbefcbf043f80bef1,0xbecfbf183f7ebec4,0x3f7fbedbbf133f7f,
0x3f2c3e95bf783f35,0xbf7d3f223eacbf7b,0x3edbbf7f3f183ec4,0x3f043ef1bf803f0e,0x3d49bf623f5c0000,0x3f4e3dc9bf673f55,0xbf713f463e16bf6d,0x3e79bf753f3e3e48,
0xbf3e3f75be79bf35,0xbe16bf463f71be48,0x3f67bdc9bf4e3f6d,0xbf5c3f62bd49bf55,0x3f80bef1bf043f80,0xbf183f7fbedbbf0e,0xbeacbf223f7dbec4,0x3f78be95bf2c3f7b,
0xbf733e793f31bf7b,0x3f58bf673dfb3f46,0x3efcbf803f133ec4,0x3eb83f18bf7f3ef1,0x3f423e16bf6a3f55,0xbf7c3f2c3e89bf75,0xbf4a3f71be60bf35,0x3cc9bf5c3f65bdc9,
0x3ea1bf783f393e48,0x3f093edbbf7e3f22,0x3f5fbd49bf513f6d,0xbf6f3f4e3d97bf62,0xbf273f7dbecfbf0e,0xbe2fbf3e3f77be95,0xbf1dbeac3f7abf35,0x3f80bf04bee63f7f,
0x3f7bbec4bf0e3f80,0xbf553f6dbe48bf35,0x3e48bf6d3f550000,0x3f0e3ec4bf7b3f35,0xbf7b3ec43f0ebf80,0x3f55bf6d3e483f35,0xbe483f6dbf550000,0xbf0ebec43f7bbf35,
0xbe483f6dbf558000,0xbf0ebec43f7bbf35,0x3f7bbec4bf0e3f80,0xbf553f6dbe48bf35,0x3e48bf6d3f558000,0x3f0e3ec4bf7b3f35,0xbf7b3ec43f0ebf80,0x3f55bf6d3e483f35,
0xbf733f4e3cc9bf55,0x3f09bf803f1d3e95,0xbefcbedb3f7cbf35,0x3f6fbe79bf273f7f,0x3f7fbf04becf3f7b,0xbf513f71be89bf22,0x3dfb3f3ebf7a3ec4,0xbf39be163f65bf62,
0xbea1bf183f80bf0e,0x3f58bd49bf4a3f75,0x3f5fbf673e2f3f35,0xbeb83f78bf42bdc9,0xbd973f5cbf6a3e48,0xbf13beac3f77bf46,0xbf7e3f2c3e60bf6d,0x3f31bf7d3ee63ef1,
0x3f67bf623e163f35,0xbf043f7fbf2cbe48,0xbd49bf463f78bec4,0x3f183e95bf713f55,0xbeac3f75bf4e0000,0xbe79bf223f80bf0e,0x3f3e3dc9bf5c3f6d,0xbf7d3ef13edbbf7b,
0x3edb3ef1bf7d3f35,0xbf5c3dc93f3ebf7b,0x3f80bf22be793f6d,0xbf4e3f75beacbf0e,0xbf713e953f18bf80,0x3f78bf46bd493f55,0xbf2c3f7fbf04bec4,0x3e16bf623f67be48,
0xbf7c3f3e3d97bf55,0x3f4abf783ecf3ef1,0xbf31be163f5fbf6d,0x3f73beacbf093f7f,0x3e60bf673f65be48,0x3e893f18bf803f22,0x3f6fbf5c3dfb3f35,0xbf273f80bf13be95,
0xbe2fbf2c3f7fbf0e,0x3f1d3e79bf6a3f62,0x3f39bf7d3efc3ec4,0xbea13f71bf583dc9,0x3f7abedbbee63f7b,0xbf773f4ebcc9bf46,0x3eb83f04bf7e3f35,0xbf42bd493f51bf75,
0xbf623e483f22bf80,0x3f7fbf0ebe953f6d,0xbf753f55bdc9bf35,0x3f46bf7b3ef13ec4,0xbef13f7bbf460000,0x3dc9bf553f75bec4,0x3e953f0ebf7f3f35,0xbf22be483f62bf6d,
0x3ef1bf7b3f468000,0xbdc93f55bf753ec4,0xbe95bf0e3f7fbf35,0x3f223e48bf623f6d,0xbf623e483f22bf80,0x3f7fbf0ebe953f6d,0xbf753f55bdc9bf35,0x3f46bf7b3ef13ec4,
0x3f393d49bf4a3f7b,0xbf653e793f13bf7f,0x3e603f18bf7f3f35,0xbefcbeac3f6fbf62,0x3f6abf673e893f0e,0xbf423f7dbf09be95,0x3f7cbf04bea13f6d,0xbf7e3f3e3cc9bf46,
0xbf313f80bf1dbe48,0x3ee6bf783f51bdc9,0xbf7a3f4ebd97bf35,0x3f5fbf713eb83ef1,0x3ecf3edbbf773f55,0xbf27be163f58bf75,0xbe2f3f5cbf733ec4,0xbdfbbf2c3f80bf22,
0xbe16bf223f80bf35,0x3eac3ef1bf783f55,0xbf04be953f67bf6d,0x3f2c3dc9bf4e3f7b,0x3f18bf7f3f3e0000,0xbedb3f75bf5c3e48,0x3e79bf623f71bec4,0xbd493f46bf7d3f0e,
0x3f7dbf463d493f35,0xbf713f62be79bf0e,0x3f5cbf753edb3ec4,0xbf3e3f7fbf18be48,0x3f4ebdc9bf2c3f80,0xbf673e953f04bf7b,0x3f78bef1beac3f6d,0xbf803f223e16bf55,
0xbf4a3f7dbf13be48,0x3f39bf803f273dc9,0xbf653f71becfbec4,0x3f58bf783efc3e95,0xbf773f5cbe60bf0e,0x3f6fbf673ea13ef1,0xbf7f3f3ebcc9bf35,0x3f7cbf4e3dfb3f22,
0xbf1dbe163f51bf7b,0x3f313d49bf423f7f,0xbee6beac3f6abf6d,0x3f093e79bf5f3f75,0xbe89bf043f7abf55,0x3eb83edbbf733f62,0xbd97bf2c3f80bf35,0x3e2f3f18bf7e3f46,
0xbf3500003f353f80,0x3f350000bf35bf80,0xbf3500003f353f80,0x3f350000bf35bf80,0xbf3500003f353f80,0x3f350000bf35bf80,0xbf3500003f353f80,0x3f350000bf35bf80,
0xbf35bf80bf358000,0x3f353f803f358000,0xbf35bf80bf358000,0x3f353f803f358000,0xbf35bf80bf358000,0x3f353f803f358000,0xbf35bf80bf358000,0x3f353f803f358000,
0x3f77bf783f7abf7b,0x3f6fbf713f73bf75,0x3f7fbf803f80bf80,0x3f7cbf7d3f7ebf7f,0x3f4abf4e3f51bf55,0x3f39bf3e3f42bf46,0x3f65bf673f6abf6d,0x3f58bf5c3f5fbf62,
0xbe893e79be603e48,0xbeb83eacbea13e95,0xbd973d49bcc98000,0xbe2f3e16bdfb3dc9,0xbf1d3f18bf133f0e,0xbf313f2cbf273f22,0xbee63edbbecf3ec4,0xbf093f04befc3ef1,
0xbf183f22bf2c3f35,0xbedb3ef1bf043f0e,0xbe793e95beac3ec4,0xbd493dc9be163e48,0xbf7d3f7fbf803f80,0xbf713f75bf783f7b,0xbf5c3f62bf673f6d,0xbf3e3f46bf4e3f55,
0x3f4ebf463f3ebf35,0x3f67bf623f5cbf55,0x3f78bf753f71bf6d,0x3f80bf7f3f7dbf7b,0x3e16bdc93d498000,0x3eacbe953e79be48,0x3f04bef13edbbec4,0x3f2cbf223f18bf0e,
0xbecf3eacbe893e48,0xbf273f18bf093ef1,0x3e2fbe793ea1bec4,0xbdfb3d493cc9bdc9,0x3f31bf3e3f4abf55,0x3ee6bf043f13bf22,0x3f7abf7d3f7fbf80,0x3f5fbf673f6fbf75,
0xbf6a3f71bf773f7b,0xbf423f4ebf583f62,0xbf7c3f78bf733f6d,0xbf7e3f80bf803f7f,0xbf393f2cbf1d3f0e,0xbf653f5cbf513f46,0xbe603e16bd978000,0xbefc3edbbeb83e95,
0xbf753f7bbf7f3f80,0xbf463f55bf623f6d,0xbef13f0ebf223f35,0xbdc93e48be953ec4,0x3e95be483dc90000,0x3f22bf0e3ef1bec4,0x3f62bf553f46bf35,0x3f7fbf7b3f75bf6d,
0x3e95be483dc98000,0x3f22bf0e3ef1bec4,0x3f62bf553f46bf35,0x3f7fbf7b3f75bf6d,0x3f75bf7b3f7fbf80,0x3f46bf553f62bf6d,0x3ef1bf0e3f22bf35,0x3dc9be483e95bec4,
0x3e60beac3ee6bf0e,0xbe893e16bcc9bdc9,0x3f6fbf783f7ebf80,0x3f27bf3e3f51bf62,0xbf7c3f80bf7f3f7b,0xbf4a3f5cbf6a3f75,0xbf313f18befc3ec4,0xbf733f67bf583f46,
0xbf7a3f71bf653f55,0xbf773f7dbf803f7f,0xbeb83e79bdfb8000,0xbf423f2cbf133ef1,0x3e2fbd49bd973e48,0x3f1dbf043ecfbe95,0xbf393f4ebf5f3f6d,0xbea13edbbf093f22,
0x3f71bf623f4ebf35,0x3f78bf7f3f80bf7b,0x3f2cbf463f5cbf6d,0x3e16be953edbbf0e,0xbf673f75bf7d3f80,0xbf043f22bf3e3f55,0x3d493dc9be793ec4,0x3f18bef13eacbe48,
0x3eacbef13f18bf35,0xbe793dc93d49be48,0xbf3e3f22bf043ec4,0xbf7d3f75bf673f55,0x3edbbe953e168000,0x3f5cbf463f2cbf0e,0x3f80bf7f3f78bf6d,0x3f4ebf623f71bf7b,
0xbd973e79becf3f0e,0x3f13bedb3e89bdc9,0xbf7e3f80bf7a3f6d,0xbf313f4ebf653f75,0xbea13e163cc9be48,0xbf583f3ebf1d3ef1,0x3f5fbf713f7cbf80,0x3eb8bf043f27bf46,
0x3f7fbf783f6abf55,0x3f51bf673f77bf7f,0x3dfb3d49be603ec4,0x3f39bf183ee6be95,0xbf733f7dbf803f7b,0xbf093f2cbf4a3f62,0xbefc3eacbe2f8000,0xbf6f3f5cbf423f22,
0xbf553f6dbf7b3f80,0xbe483ec4bf0e3f35,0x3f0ebec43e480000,0x3f7bbf6d3f55bf35,0x3f55bf6d3f7bbf80,0x3e48bec43f0ebf35,0xbf0e3ec4be480000,0xbf7b3f6dbf553f35,
0x3f0ebec43e488000,0x3f7bbf6d3f55bf35,0x3f55bf6d3f7bbf80,0x3e48bec43f0ebf35,0xbf0e3ec4be488000,0xbf7b3f6dbf553f35,0xbf553f6dbf7b3f80,0xbe483ec4bf0e3f35,
0xbf423f18becf3e48,0xbf7c3f80bf773f62,0x3f4abf673f7abf80,0x3cc9be793ee6bf22,0x3f73bf5c3f39bf0e,0x3f58bf713f7ebf7f,0xbefc3f2cbf513f6d,0x3eb8be16bd973e95,
0xbf273f4ebf6a3f7b,0x3e2f3d49be893ef1,0xbf1d3edbbe608000,0xbf803f78bf653f46,0x3ea1bf043f31bf55,0xbf093eacbdfbbdc9,0x3f5fbf3e3f13bec4,0x3f6fbf7d3f7fbf75,
0x3d49be953f04bf35,0xbf4e3f22bedb3e48,0xbf713f7fbf7d3f6d,0xbe793ef1bf2c3f55,0xbf3e3f62bf783f80,0x3e163dc9beac3f0e,0x3f67bf463f18bec4,0x3f5cbf753f80bf7b,
0xbf803f75bf5c3f35,0xbf183f46bf673f7b,0x3eacbdc9be163ec4,0x3f78bf623f3ebf0e,0x3f2cbef13e798000,0x3f7dbf7f3f71bf55,0x3edbbf223f4ebf6d,0xbf043e95bd49be48,
0x3f09bf3e3f65bf7b,0xbefc3e793cc9be95,0x3ecfbe16bdfb3ec4,0x3f7fbf713f51bf22,0xbf7c3f67bf423f0e,0xbf1d3f4ebf6f3f7f,0x3f31bf5c3f77bf80,0xbea13d493e60bef1,
0xbf583f2cbee63e48,0xbf5f3f78bf803f75,0x3f6abf7d3f7ebf6d,0x3d97beac3f13bf46,0xbe2f3edbbf273f55,0x3f4abf183eb8bdc9,0xbf393f04be898000,0xbf733f80bf7a3f62,
0xbf223f55bf753f80,0x3ef1be48bdc93ec4,0x3f7fbf7b3f62bf35,0x3e95bf0e3f46bf6d,0xbf463f0ebe950000,0xbf623f7bbf7f3f6d,0x3dc93e48bef13f35,0x3f75bf553f22bec4,
0x3f46bf0e3e958000,0x3f62bf7b3f7fbf6d,0xbdc9be483ef1bf35,0xbf753f55bf223ec4,0xbf223f55bf753f80,0x3ef1be48bdc93ec4,0x3f7fbf7b3f62bf35,0x3e95bf0e3f46bf6d,
0xbf6f3f80bf773f55,0x3d973e79bf093f46,0x3f13bf4e3f73bf80,0xbf1d3eacbcc9be95,0xbf313edbbdfbbe48,0xbf653f7dbf7c3f62,0x3f7abf5c3f27bec4,0x3efcbf3e3f6abf7f,
0x3eb8bd49be893f0e,0x3f7fbf783f58bf22,0xbf513f18bea18000,0xbf4a3f71bf803f75,0xbf393f67bf7e3f7b,0x3ee6be16be2f3ef1,0x3e60bf043f42bf6d,0xbf5f3f2cbecf3dc9,
0xbf783f7fbf673f35,0x3d493e95bf183f55,0x3f7dbf623f2cbec4,0x3eacbf223f5cbf7b,0xbf043f46bf713f80,0x3f3ebef13e163e48,0x3f4ebf753f80bf6d,0xbedb3dc93e79bf0e,
0x3e793dc9bedb3f35,0x3f80bf753f4ebf0e,0x3e16bef13f3ebf6d,0xbf713f46bf043e48,0x3f5cbf223eac8000,0x3f2cbf623f7dbf7b,0xbf183e953d49bec4,0xbf673f7fbf783f55,
0xbf5f3f7dbf7a3f55,0x3ecfbd49bea13f22,0x3f42bf713f80bf6d,0xbf133e793dfbbef1,0xbf1d3f5cbf7c3f7b,0x3f39bedb3d973e95,0x3ee6bf3e3f6fbf80,0xbf583f18be89bdc9,
0x3efcbe16be603f0e,0x3f6abf803f73bf46,0xbf273eac3cc9bec4,0xbf513f78bf7e3f62,0x3f4abf043e2f3e48,0x3f31bf673f7fbf75,0xbf653f2cbeb88000,0xbf093f4ebf773f7f,
0xbec43f35bf6d3f80,0x3f6dbf353ec40000,0x3ec4bf353f6dbf80,0xbf6d3f35bec40000,0xbec43f35bf6d3f80,0x3f6dbf353ec40000,0x3ec4bf353f6dbf80,0xbf6d3f35bec40000,
0x3f6dbf353ec48000,0x3ec4bf353f6dbf80,0xbf6d3f35bec48000,0xbec43f35bf6d3f80,0x3f6dbf353ec48000,0x3ec4bf353f6dbf80,0xbf6d3f35bec48000,0xbec43f35bf6d3f80,
0xbdfb3f04bf513f7b,0x3f80bf673f27be95,0x3ea1bf2c3f6abf80,0xbf7a3f4ebefc3dc9,0x3e893e16bf093f55,0x3f6fbf803f65bf22,0xbd97beac3f31bf6d,0xbf7c3f78bf4a3ef1,
0x3f7ebf5c3f13be48,0x3cc9bedb3f42bf75,0xbf733f3ebecf8000,0xbe603f18bf5f3f7f,0x3f77bf7d3f58bf0e,0xbeb8bd493ee6bf46,0xbf7f3f71bf393ec4,0x3e2f3e79bf1d3f62,
0x3f04bdc9beac3f35,0x3f3ebf753f7dbf55,0xbf4e3ef1bd49bec4,0xbedb3f46bf783f7b,0xbe793f22bf673f80,0x3f80bf623f18be48,0xbe16be953f2cbf6d,0xbf713f7fbf5c3f0e,
0x3f5cbf7f3f71bf35,0xbf2c3e953e16bf0e,0xbf183f62bf803f6d,0x3f67bf223e793e48,0x3f78bf463edb8000,0x3d49bef13f4ebf7b,0xbf7d3f75bf3e3ec4,0x3eac3dc9bf043f55,
0x3f80bf673f1dbe48,0xbea1be163f13bf62,0xbf583f04bd97bec4,0xbe893f2cbf6f3f7f,0x3ecf3d49befc3f55,0x3f42bf783f7abf46,0x3e2fbf183f65bf80,0xbf7e3f71bf313e95,
0xbcc9bedb3f4abf7b,0xbf733f7dbf513ef1,0xbf093f5cbf7f3f6d,0x3f77bf3e3eb83dc9,0x3f6abf803f5fbf0e,0xbf273e793e60bf22,0xbf7c3f4ebee68000,0x3dfb3eacbf393f75,
0xbdc93f0ebf623f80,0x3f75bf7b3f46bec4,0xbf223e483e95bf35,0xbef13f55bf7f3f6d,0x3f7fbf553ef10000,0xbe95be483f22bf6d,0xbf463f7bbf753f35,0x3f62bf0e3dc93ec4,
0x3f7fbf553ef18000,0xbe95be483f22bf6d,0xbf463f7bbf753f35,0x3f62bf0e3dc93ec4,0x3dc9bf0e3f62bf80,0xbf753f7bbf463ec4,0x3f22be48be953f35,0x3ef1bf553f7fbf6d,
0x3f51bedbbd973f0e,0x3dfbbf183f6abf7f,0x3cc9bf043f5fbf80,0xbf653f80bf583ef1,0x3e60bf2c3f73bf7b,0xbf773f78bf393e95,0xbf6f3f7dbf4a3ec4,0x3f42beacbe2f3f22,
0x3f13bf673f7fbf55,0xbf7e3f4ebecfbdc9,0xbf803f5cbefc8000,0x3ee63d49bf093f62,0xbf7a3f3ebea1be48,0x3e893e79bf313f75,0x3eb83e16bf1d3f6d,0x3f27bf713f7cbf46,
0x3f2cbf753f78bf35,0xbf7d3f46beacbe48,0x3edb3dc9bf183f6d,0x3f04bf623f80bf55,0x3d493ef1bf5c3f80,0x3f4ebf7f3f67bf0e,0xbf713f22be16bec4,0x3e793e95bf3e3f7b,
0xbf3e3e953e79bf35,0xbe163f22bf713f7b,0x3f67bf7f3f4ebec4,0xbf5c3ef13d49bf0e,0x3f80bf623f048000,0xbf183dc93edbbf55,0xbeac3f46bf7d3f6d,0x3f78bf753f2cbe48,
0xbf653f043cc9bf0e,0x3e603eacbf4a3f7f,0xbe893f3ebf7c3f6d,0x3f6abf7d3f42be95,0x3f7fbf4e3eb83e48,0xbf133d493efcbf62,0xbdfbbedb3f58bf80,0xbf313f78bf733f22,
0xbee63f5cbf803f55,0x3f7abf713f1dbdc9,0x3f77bf2c3e2f3ec4,0xbecfbe163f27bf75,0x3d97bf183f6fbf7b,0xbf513f80bf5f3ef1,0xbf7e3f67bf098000,0x3f39be79bea13f46,
0x3e483ec4bf553f80,0x3f0ebf6d3f7bbf35,0xbf7b3f6dbf0e0000,0x3f55bec4be483f35,0xbe48bec43f55bf80,0xbf0e3f6dbf7b3f35,0x3f7bbf6d3f0e0000,0xbf553ec43e48bf35,
0x3f7bbf6d3f0e8000,0xbf553ec43e48bf35,0x3e483ec4bf553f80,0x3f0ebf6d3f7bbf35,0xbf7b3f6dbf0e8000,0x3f55bec4be483f35,0xbe48bec43f55bf80,0xbf0e3f6dbf7b3f35,
0x3f65bf7d3f39be48,0xbf7a3f2cbdfbbef1,0xbe89beac3f51bf80,0xbecf3f5cbf7f3f46,0xbf273f78bf6f3f0e,0x3f7cbf673efc3dc9,0x3f1dbd49bf093f6d,0x3cc9bf183f73bf75,
0xbee6be163f31bf7b,0xbe603f3ebf7e3f62,0xbf773f71bf138000,0x3f6abf04bd973f22,0x3f42be79beb83f55,0xbe2fbedb3f5fbf7f,0x3f4abf803f58bec4,0xbf803f4ebea1be95,
0xbf673ef13e16bf35,0x3f043dc9bf2c3f7b,0x3d49bf223f78bf6d,0xbf183f75bf713f0e,0x3eac3e95bf4e3f80,0x3e79bf463f80bf55,0xbf3e3f7fbf5c3ec4,0x3f7dbf623edb3e48,
0xbedb3f62bf7d3f35,0x3f5cbf7f3f3ebe48,0xbf803f46be79bec4,0x3f4ebe95beac3f55,0x3f71bf753f188000,0xbf783f22bd49bf0e,0x3f2cbdc9bf043f6d,0xbe16bef13f67bf7b,
0x3f133d49bf273f7b,0xbdfbbf043f6fbf75,0x3f80bf4e3e893ec4,0xbf653edb3e60bf46,0x3f09bf713f73bf0e,0xbf5f3f7dbf313dc9,0xbecfbe793f4abf80,0xbd973f2cbf7c3f62,
0x3f51bf803f42be48,0xbf7e3f5cbeb8be95,0xbcc9bf183f77bf6d,0xbee63f67bf7a3f22,0xbf583eac3ea1bf55,0x3efc3e16bf393f7f,0xbf6a3f78bf1d8000,0x3f7fbf3e3e2f3ef1,
0x3ef13e48bf463f80,0xbdc9bf0e3f75bf6d,0xbe953f55bf7f3f35,0x3f22bf7b3f62bec4,0xbf623f7bbf220000,0x3f7fbf553e953ec4,0xbf753f0e3dc9bf35,0x3f46be48bef13f6d,
0x3f62bf7b3f228000,0xbf7f3f55be95bec4,0x3f75bf0ebdc93f35,0xbf463e483ef1bf6d,0x3ef13e48bf463f80,0xbdc9bf0e3f75bf6d,0xbe953f55bf7f3f35,0x3f22bf7b3f62bec4,
0x3cc9bf2c3f7ebf55,0xbea13f5cbf7c3f22,0xbf09be163f42bf80,0x3e893edbbf6a3f75,0x3f6fbf713efc3e48,0xbf7f3f4ebe60bef1,0x3f13bf783f65bec4,0xbf4a3f80bf393dc9,
0xbf803f3ebdfbbf0e,0x3f73bf04be2f3f46,0xbf583f7dbf278000,0x3f77bf673ecf3e95,0xbeb8beac3f5fbf7b,0x3d973f18bf7a3f62,0xbf513e793ee6bf6d,0x3f1d3d49bf313f7f,
0xbe163f46bf803f35,0x3eacbf623f78bf0e,0xbf043f75bf673ec4,0x3f2cbf7f3f4ebe48,0x3f183dc9bf3e3f80,0xbedbbe953f5cbf7b,0x3e793ef1bf713f6d,0xbd49bf223f7dbf55,
0x3f7dbf22bd493f35,0xbf713ef13e79bf55,0x3f5cbe95bedb3f6d,0xbf3e3dc93f18bf7b,0x3f4ebf7f3f2c8000,0xbf673f75bf04be48,0x3f78bf623eac3ec4,0xbf803f46be16bf0e,
0xbdfbbf183f7cbf55,0x3cc93f2cbf7f3f46,0xbea1bedb3f6fbf6d,0x3e603f04bf773f62,0xbefcbe793f58bf7b,0x3ecf3eacbf653f75,0xbf27bd493f39bf80,0x3f133e16bf4a3f7f,
0xbf7e3f4ebe2fbf0e,0x3f80bf3e3d973f22,0xbf733f67beb8bec4,0x3f7abf5c3e893ef1,0xbf5f3f78bf09be48,0x3f6abf713ee63e95,0xbf423f80bf318000,0x3f51bf7d3f1d3dc9,
0xbf3500003f353f80,0x3f350000bf35bf80,0xbf3500003f353f80,0x3f350000bf35bf80,0xbf3500003f353f80,0x3f350000bf35bf80,0xbf3500003f353f80,0x3f350000bf35bf80,
0xbf35bf80bf358000,0x3f353f803f358000,0xbf35bf80bf358000,0x3f353f803f358000,0xbf35bf80bf358000,0x3f353f803f358000,0xbf35bf80bf358000,0x3f353f803f358000,
0x3efcbf043f09bf0e,0x3ecfbedb3ee6bef1,0x3f27bf2c3f31bf35,0x3f13bf183f1dbf22,0x3dfbbe163e2fbe48,0x3cc9bd493d97bdc9,0x3ea1beac3eb8bec4,0x3e60be793e89be95,
0xbf5f3f5cbf583f55,0xbf6a3f67bf653f62,0xbf423f3ebf393f35,0xbf513f4ebf4a3f46,0xbf7e3f7dbf7c3f7b,0xbf803f80bf7f3f7f,0xbf733f71bf6f3f6d,0xbf7a3f78bf773f75,
0x3f4ebf463f3ebf35,0x3f67bf623f5cbf55,0x3f78bf753f71bf6d,0x3f80bf7f3f7dbf7b,0x3e16bdc93d490000,0x3eacbe953e79be48,0x3f04bef13edbbec4,0x3f2cbf223f18bf0e,
0x3f18bf223f2cbf35,0x3edbbef13f04bf0e,0x3e79be953eacbec4,0x3d49bdc93e16be48,0x3f7dbf7f3f80bf80,0x3f71bf753f78bf7b,0x3f5cbf623f67bf6d,0x3f3ebf463f4ebf55,
0xbeb83edbbefc3f0e,0xbd973e16be603e95,0xbf513f5cbf653f6d,0xbf1d3f2cbf393f46,0xbf803f80bf7e3f7b,0xbf733f78bf7c3f7f,0xbf583f4ebf423f35,0xbf773f71bf6a3f62,
0x3f6fbf673f5fbf55,0x3f7fbf7d3f7abf75,0x3f13bf043ee6bec4,0x3f4abf3e3f31bf22,0x3cc93d49bdfb3e48,0x3ea1be793e2fbdc9,0xbf093f18bf273f35,0xbe893eacbecf3ef1,
0x3f75bf7b3f7fbf80,0x3f46bf553f62bf6d,0x3ef1bf0e3f22bf35,0x3dc9be483e95bec4,0xbe953e48bdc90000,0xbf223f0ebef13ec4,0xbf623f55bf463f35,0xbf7f3f7bbf753f6d,
0xbe953e48bdc98000,0xbf223f0ebef13ec4,0xbf623f55bf463f35,0xbf7f3f7bbf753f6d,0xbf753f7bbf7f3f80,0xbf463f55bf623f6d,0xbef13f0ebf223f35,0xbdc93e48be953ec4,
0x3f09bedb3ea1be48,0x3f5fbf4e3f39bf22,0xbecf3f04bf1d3f35,0x3d973d49be2f3e95,0x3f13bf2c3f42bf55,0x3dfbbe793eb8bef1,0x3f80bf7d3f77bf6d,0x3f65bf713f7abf7f,
0x3f58bf673f73bf7b,0x3efcbf183f31bf46,0x3f6abf5c3f4abf35,0x3f7fbf803f7cbf75,0xbf513f3ebf273f0e,0xbf7e3f78bf6f3f62,0x3cc9be163e89bec4,0xbee63eacbe603dc9,
0xbeac3ef1bf183f35,0x3e79bdc9bd493e48,0x3f3ebf223f04bec4,0x3f7dbf753f67bf55,0xbedb3e95be160000,0xbf5c3f46bf2c3f0e,0xbf803f7fbf783f6d,0xbf4e3f62bf713f7b,
0x3f71bf623f4ebf35,0x3f78bf7f3f80bf7b,0x3f2cbf463f5cbf6d,0x3e16be953edbbf0e,0xbf673f75bf7d3f80,0xbf043f22bf3e3f55,0x3d493dc9be793ec4,0x3f18bef13eacbe48,
0xbf423f5cbf6f3f7b,0xbe2f3eacbefc3f22,0xbf4a3f2cbf093ec4,0xbf803f7dbf733f62,0x3ee6bf183f39bf55,0xbe603d493dfbbe95,0x3f77bf673f51bf35,0x3f6abf783f7fbf7f,
0x3f27bf043eb8be48,0x3f7cbf713f5fbf46,0xbf1d3f3ebf583f6d,0x3cc93e16bea13ef1,0xbf653f4ebf313f0e,0xbf7a3f80bf7e3f75,0x3e89bedb3f13bf35,0xbecf3e79bd97bdc9,
0xbf553f6dbf7b3f80,0xbe483ec4bf0e3f35,0x3f0ebec43e480000,0x3f7bbf6d3f55bf35,0x3f55bf6d3f7bbf80,0x3e48bec43f0ebf35,0xbf0e3ec4be480000,0xbf7b3f6dbf553f35,
0x3f0ebec43e488000,0x3f7bbf6d3f55bf35,0x3f55bf6d3f7bbf80,0x3e48bec43f0ebf35,0xbf0e3ec4be488000,0xbf7b3f6dbf553f35,0xbf553f6dbf7b3f80,0xbe483ec4bf0e3f35,
0xbf7f3f7dbf6f3f55,0xbf133f3ebf5f3f75,0x3dfbbeac3f09bf35,0xbf313f04bea13dc9,0x3f65bf783f80bf7b,0x3e60bedb3f1dbf46,0x3e89bd49be2f3ec4,0x3f6abf4e3f27bef1,
0x3d973e16beb83f0e,0x3f51bf2c3efcbe95,0xbf7e3f71bf583f35,0xbf393f5cbf733f7f,0xbee63e79bcc9be48,0xbf7a3f67bf4a3f22,0x3f77bf803f7cbf6d,0x3ecfbf183f42bf62,
0xbf803f75bf5c3f35,0xbf183f46bf673f7b,0x3eacbdc9be163ec4,0x3f78bf623f3ebf0e,0x3f2cbef13e790000,0x3f7dbf7f3f71bf55,0x3edbbf223f4ebf6d,0xbf043e95bd49be48,
0xbd493e95bf043f35,0x3f4ebf223edbbe48,0x3f71bf7f3f7dbf6d,0x3e79bef13f2cbf55,0x3f3ebf623f78bf80,0xbe16bdc93eacbf0e,0xbf673f46bf183ec4,0xbf5c3f75bf803f7b,
0xbf7a3f80bf733f55,0xbe893f04bf393f62,0x3eb8bf183f4abf6d,0xbf273edbbe2fbdc9,0x3f13beac3d973e48,0x3f7ebf7d3f6abf46,0xbf803f78bf5f3f35,0xbee63f2cbf583f75,
0x3e603d49bea13f0e,0x3f77bf5c3f31bef1,0xbf6f3f4ebf1d3ec4,0xbf423f67bf7c3f7f,0x3f51bf713f7fbf7b,0xbdfbbe163ecfbf22,0x3cc93e79befc3f35,0x3f65bf3e3f09be95,
0x3f22bf553f75bf80,0xbef13e483dc9bec4,0xbf7f3f7bbf623f35,0xbe953f0ebf463f6d,0x3f46bf0e3e950000,0x3f62bf7b3f7fbf6d,0xbdc9be483ef1bf35,0xbf753f55bf223ec4,
0xbf463f0ebe958000,0xbf623f7bbf7f3f6d,0x3dc93e48bef13f35,0x3f75bf553f22bec4,0x3f22bf553f75bf80,0xbef13e483dc9bec4,0xbf7f3f7bbf623f35,0xbe953f0ebf463f6d,
0x3ecfbf2c3f5fbf7b,0xbf423f04be60bdc9,0x3e2f3e16bee63f35,0x3f7ebf673f39bef1,0x3f80bf713f4abf0e,0x3ea1bf183f51bf75,0xbf583f78bf7f3f6d,0x3e893d49beb83f22,
0xbf6a3f3ebefc3e48,0xbf273f5cbf7a3f7f,0x3f7cbf7d3f65bf35,0x3dfbbedb3f31bf62,0x3cc9beac3f1dbf55,0xbf733f4ebf133e95,0x3f09be79bd973ec4,0x3f77bf803f6fbf46,
0xbe79bdc93edbbf35,0xbf803f75bf4e3f0e,0xbe163ef1bf3e3f6d,0x3f71bf463f04be48,0xbf5c3f22beac0000,0xbf2c3f62bf7d3f7b,0x3f18be95bd493ec4,0x3f67bf7f3f78bf55,
0xbf783f7fbf673f35,0x3d493e95bf183f55,0x3f7dbf623f2cbec4,0x3eacbf223f5cbf7b,0xbf043f46bf713f80,0x3f3ebef13e163e48,0x3f4ebf753f80bf6d,0xbedb3dc93e79bf0e,
0xbf773f4ebf093e48,0xbeb83f2cbf653f7f,0x3f7fbf673f31bec4,0x3e2fbf043f4abf75,0xbf7e3f78bf513f0e,0x3cc93eacbf273f62,0x3f73bf803f6abf35,0xbe60be163efcbf46,
0xbe893f18bf583f7b,0x3f6fbf3e3ee6bdc9,0x3d97bedb3f39bf6d,0xbf7c3f5cbf1d3e95,0x3dfb3e79bf133f55,0x3f80bf713f42bef1,0xbea1bd493ecfbf35,0xbf7a3f7dbf5f3f22,
0xbec43f35bf6d3f80,0x3f6dbf353ec40000,0x3ec4bf353f6dbf80,0xbf6d3f35bec40000,0xbec43f35bf6d3f80,0x3f6dbf353ec40000,0x3ec4bf353f6dbf80,0xbf6d3f35bec40000,
0x3f6dbf353ec48000,0x3ec4bf353f6dbf80,0xbf6d3f35bec48000,0xbec43f35bf6d3f80,0x3f6dbf353ec48000,0x3ec4bf353f6dbf80,0xbf6d3f35bec48000,0xbec43f35bf6d3f80,
0x3f1dbe79be2f3f0e,0x3f39bf713f7fbf62,0xbee63d493eb8bf35,0xbf583f7dbf773f46,0x3f5fbf183e603e48,0x3ecfbf3e3f73bf7f,0xbf423edbbcc9bec4,0xbf133f5cbf7e3f75,
0x3f4abf783f7cbf55,0xbf313eac3d97bef1,0xbf653f80bf6f3f35,0x3f09be16be893f22,0x3efcbf4e3f7abf7b,0xbf6a3f2cbea1bdc9,0xbf273f67bf803f6d,0x3f51bf043dfb3e95,
0x3f5cbf7f3f71bf35,0xbf2c3e953e16bf0e,0xbf183f62bf803f6d,0x3f67bf223e793e48,0x3f78bf463edb0000,0x3d49bef13f4ebf7b,0xbf7d3f75bf3e3ec4,0x3eac3dc9bf043f55,
0xbf043dc93eacbf35,0xbf3e3f75bf7d3f55,0x3f4ebef13d493ec4,0x3edbbf463f78bf7b,0x3e79bf223f67bf80,0xbf803f62bf183e48,0x3e163e95bf2c3f6d,0x3f71bf7f3f5cbf0e,
0xbf393eac3dfbbf0e,0xbee63f4ebf7c3f75,0x3e603e79bf273f6d,0x3f5fbf803f6abf22,0x3eb8bf3e3f77bf7b,0xbf7f3f5cbf093dc9,0xbf513f7dbf733f35,0x3f4abedbbcc93ef1,
0xbf313f71bf7e3f55,0x3f65bf183e2f3e95,0x3f7abf783f42bec4,0xbefc3d493ecfbf46,0xbf6f3f2cbe89be48,0xbd973f04bf583f7f,0x3f13be16bea13f35,0x3f1dbf673f80bf62,
0x3dc9bf0e3f62bf80,0xbf753f7bbf463ec4,0x3f22be48be953f35,0x3ef1bf553f7fbf6d,0xbf7f3f55bef10000,0x3e953e48bf223f6d,0x3f46bf7b3f75bf35,0xbf623f0ebdc9bec4,
0xbf7f3f55bef18000,0x3e953e48bf223f6d,0x3f46bf7b3f75bf35,0xbf623f0ebdc9bec4,0xbdc93f0ebf623f80,0x3f75bf7b3f46bec4,0xbf223e483e95bf35,0xbef13f55bf7f3f6d,
0xbf7c3f71bf273e48,0x3f1dbe16beb83f46,0x3f31be79be893f35,0x3ea1bf3e3f7abf75,0x3f09bd49bee63f55,0x3efcbf5c3f80bf62,0x3ecfbf4e3f7ebf6d,0xbf7f3f67bf133dc9,
0x3e2f3eacbf423f7b,0x3f4abf7d3f6fbf22,0x3f39bf783f77bf35,0xbf733f2cbe60be95,0x3f58bf803f65bf0e,0xbf5f3f04bcc9bef1,0xbf6a3f18bdfbbec4,0x3d973edbbf513f7f,
0x3f3ebe95be793f35,0x3e16bf223f71bf7b,0xbf673f7fbf4e3ec4,0x3f5cbef1bd493f0e,0xbf803f62bf040000,0x3f18bdc9bedb3f55,0x3eacbf463f7dbf6d,0xbf783f75bf2c3e48,
0x3f2cbf753f78bf35,0xbf7d3f46beacbe48,0x3edb3dc9bf183f6d,0x3f04bf623f80bf55,0x3d493ef1bf5c3f80,0x3f4ebf7f3f67bf0e,0xbf713f22be16bec4,0x3e793e95bf3e3f7b,
0xbea1be793f39bf7b,0xbf093f67bf7e3f46,0xbf5f3f80bf513ec4,0x3f6fbf183d973ef1,0x3f27be16becf3f55,0x3e2fbf2c3f77bf75,0x3f1dbf713f7abf35,0xbf803f5cbee6bdc9,
0xbf733f78bf313e48,0x3f58bedbbdfb3f22,0x3efc3d49bf133f6d,0x3eb8bf4e3f7fbf62,0x3f42bf7d3f6abf0e,0xbf7c3f3ebe89be95,0xbf4a3eac3e60bf35,0x3cc93f04bf653f7f,
0x3e483ec4bf553f80,0x3f0ebf6d3f7bbf35,0xbf7b3f6dbf0e0000,0x3f55bec4be483f35,0xbe48bec43f55bf80,0xbf0e3f6dbf7b3f35,0x3f7bbf6d3f0e0000,0xbf553ec43e48bf35,
0x3f7bbf6d3f0e8000,0xbf553ec43e48bf35,0x3e483ec4bf553f80,0x3f0ebf6d3f7bbf35,0xbf7b3f6dbf0e8000,0x3f55bec4be483f35,0xbe48bec43f55bf80,0xbf0e3f6dbf7b3f35,
0x3ea1bf4e3f80bf55,0xbf583f80bf4a3e95,0xbf5f3edb3e2fbf35,0x3eb83e79bf423f7f,0x3d973f04bf6a3f7b,0x3f13bf713f77bf22,0x3f7ebf3e3e603ec4,0xbf313e163ee6bf62,
0xbf733f18bcc9bf0e,0x3f093d49bf1d3f75,0xbefc3f67bf7c3f35,0x3f6fbf783f27bdc9,0x3f7fbf5c3ecf3e48,0xbf513eac3e89bf46,0x3dfbbf2c3f7abf6d,0xbf393f7dbf653ef1,
0xbedb3f62bf7d3f35,0x3f5cbf7f3f3ebe48,0xbf803f46be79bec4,0x3f4ebe95beac3f55,0x3f71bf753f180000,0xbf783f22bd49bf0e,0x3f2cbdc9bf043f6d,0xbe16bef13f67bf7b,
0x3f67bef1be163f35,0xbf04bdc93f2cbf7b,0xbd493f22bf783f6d,0x3f18bf753f71bf0e,0xbeacbe953f4ebf80,0xbe793f46bf803f55,0x3f3ebf7f3f5cbec4,0xbf7d3f62bedbbe48,
0x3e2fbf3e3f7fbf55,0xbf1d3f78bf6a3ef1,0xbf393e163efcbf6d,0x3ea13eacbf583f7f,0xbf7a3f67bee6be48,0x3f77bf18bcc93f22,0xbeb83f5cbf7e3f35,0x3f42bf803f51be95,
0xbf7c3f2cbd97bf0e,0x3f4abe79becf3f62,0xbf313f7dbf5f3ec4,0x3f73bf713f093dc9,0x3e603edbbf653f7b,0x3e89bf4e3f80bf46,0x3f6fbf04bdfb3f35,0xbf273d493f13bf75,
0xbef1be483f46bf80,0x3dc93f0ebf753f6d,0x3e95bf553f7fbf35,0xbf223f7bbf623ec4,0x3f62bf7b3f220000,0xbf7f3f55be95bec4,0x3f75bf0ebdc93f35,0xbf463e483ef1bf6d,
0xbf623f7bbf228000,0x3f7fbf553e953ec4,0xbf753f0e3dc9bf35,0x3f46be48bef13f6d,0xbef1be483f46bf80,0x3dc93f0ebf753f6d,0x3e95bf553f7fbf35,0xbf223f7bbf623ec4,
0x3f31bd49bf1d3f7b,0xbee6be793f51bf7f,0x3f7abf18bd973f35,0xbf5f3eac3eb8bf62,0xbecf3f67bf773f0e,0x3f27bf7d3f58be95,0x3e2f3f04bf733f6d,0x3dfbbf3e3f80bf46,
0x3f39bf803f4abe48,0xbf653f78bf13bdc9,0x3e60bf4e3f7fbf35,0xbefc3f71bf6f3ef1,0x3f6abedbbe893f55,0xbf423e163f09bf75,0x3f7cbf5c3ea13ec4,0xbf7e3f2cbcc9bf22,
0xbf7d3f223d49bf35,0x3f71bef1be793f55,0xbf5c3e953edbbf6d,0x3f3ebdc9bf183f7b,0xbf4e3f7fbf2c0000,0x3f67bf753f043e48,0xbf783f62beacbec4,0x3f80bf463e163f0e,
0xbe163f46bf803f35,0x3eacbf623f78bf0e,0xbf043f75bf673ec4,0x3f2cbf7f3f4ebe48,0x3f183dc9bf3e3f80,0xbedbbe953f5cbf7b,0x3e793ef1bf713f6d,0xbd49bf223f7dbf55,
0x3f1dbf7d3f51be48,0xbf313f80bf423dc9,0x3ee6bf713f6abec4,0xbf093f78bf5f3e95,0x3e89bf5c3f7abf0e,0xbeb83f67bf733ef1,0x3d97bf3e3f80bf35,0xbe2f3f4ebf7e3f22,
0xbf4a3e163f13bf7b,0x3f39bd49bf273f7f,0xbf653eac3ecfbf6d,0x3f58be79befc3f75,0xbf773f043e60bf55,0x3f6fbedbbea13f62,0xbf7f3f2c3cc9bf35,0x3f7cbf18bdfb3f46,
0x3f350000bf353f80,0xbf3500003f35bf80,0x3f350000bf353f80,0xbf3500003f35bf80,0x3f350000bf353f80,0xbf3500003f35bf80,0x3f350000bf353f80,0xbf3500003f35bf80,
0xbf353f80bf358000,0x3f35bf803f358000,0xbf353f80bf358000,0x3f35bf803f358000,0xbf353f80bf358000,0x3f35bf803f358000,0xbf353f80bf358000,0x3f35bf803f358000,
0x3e893f78be60bf7b,0x3eb83f71bea1bf75,0x3d973f80bcc9bf80,0x3e2f3f7dbdfbbf7f,0x3f1d3f4ebf13bf55,0x3f313f3ebf27bf46,0x3ee63f67becfbf6d,0x3f093f5cbefcbf62,
0x3f77be79bf7a3e48,0x3f6fbeacbf733e95,0x3f7fbd49bf808000,0x3f7cbe16bf7e3dc9,0x3f4abf18bf513f0e,0x3f39bf2cbf423f22,0x3f65bedbbf6a3ec4,0x3f58bf04bf5f3ef1,
0xbf4ebf223f3e3f35,0xbf67bef13f5c3f0e,0xbf78be953f713ec4,0xbf80bdc93f7d3e48,0xbe16bf7f3d493f80,0xbeacbf753e793f7b,0xbf04bf623edb3f6d,0xbf2cbf463f183f55,
0xbf183f463f2cbf35,0xbedb3f623f04bf55,0xbe793f753eacbf6d,0xbd493f7f3e16bf7b,0xbf7d3dc93f808000,0xbf713e953f78be48,0xbf5c3ef13f67bec4,0xbf3e3f223f4ebf0e,
0x3f6abeacbf773e48,0x3f42bf18bf583ef1,0x3f7c3e79bf73bec4,0x3f7ebd49bf80bdc9,0x3f393f3ebf1dbf55,0x3f653f04bf51bf22,0x3e603f7dbd97bf80,0x3efc3f67beb8bf75,
0xbecfbf713e893f7b,0xbf27bf4e3f093f62,0x3e2fbf78bea13f6d,0xbdfbbf80bcc93f7f,0x3f31bf2cbf4a3f0e,0x3ee6bf5cbf133f46,0x3f7abe16bf7f8000,0x3f5fbedbbf6f3e95,
0xbe95bf7b3dc93f80,0xbf22bf553ef13f6d,0xbf62bf0e3f463f35,0xbf7fbe483f753ec4,0xbf753e483f7f0000,0xbf463f0e3f62bec4,0xbef13f553f22bf35,0xbdc93f7b3e95bf6d,
0xbf753e483f7f8000,0xbf463f0e3f62bec4,0xbef13f553f22bf35,0xbdc93f7b3e95bf6d,0x3e953f7bbdc9bf80,0x3f223f55bef1bf6d,0x3f623f0ebf46bf35,0x3f7f3e48bf75bec4,
0x3f7a3eacbf65bf0e,0x3f77be16bf80bdc9,0x3eb83f78bdfbbf80,0x3f423f3ebf13bf62,0xbe2fbf80bd973f7b,0xbf1dbf5c3ecf3f75,0x3f39bf18bf5f3ec4,0x3ea1bf67bf093f46,
0x3e60bf71bee63f55,0xbe89bf7d3cc93f7f,0x3f6fbe79bf7e8000,0x3f27bf2cbf513ef1,0xbf7c3d493f7f3e48,0xbf4a3f043f6abe95,0xbf31bf4e3efc3f6d,0xbf73bedb3f583f22,
0xbeac3f623f18bf35,0x3e793f7f3d49bf7b,0x3f3e3f46bf04bf6d,0x3f7d3e95bf67bf0e,0xbedbbf753e163f80,0xbf5cbf223f2c3f55,0xbf80bdc93f783ec4,0xbf4e3ef13f71be48,
0x3f713ef1bf4ebf35,0x3f78bdc9bf80be48,0x3f2cbf22bf5c3ec4,0x3e16bf75bedb3f55,0xbf673e953f7d8000,0xbf043f463f3ebf0e,0x3d493f7f3e79bf6d,0x3f183f62beacbf7b,
0xbf7fbe793f6a3f0e,0xbf513edb3f77bdc9,0xbdfbbf80be603f6d,0xbf39bf4e3ee63f75,0x3f73be16bf80be48,0x3f09bf3ebf4a3ef1,0x3efc3f71be2fbf80,0x3f6f3f04bf42bf46,
0xbd973f783ecfbf55,0x3f133f67be89bf7f,0xbf7ebd493f7a3ec4,0xbf313f183f65be95,0xbea1bf7dbcc93f7b,0xbf58bf2c3f1d3f62,0x3f5fbeacbf7c8000,0x3eb8bf5cbf273f22,
0xbf0ebf6d3e483f80,0xbf7bbec43f553f35,0xbf553ec43f7b0000,0xbe483f6d3f0ebf35,0x3f0e3f6dbe48bf80,0x3f7b3ec4bf55bf35,0x3f55bec4bf7b0000,0x3e48bf6dbf0e3f35,
0xbf553ec43f7b8000,0xbe483f6d3f0ebf35,0x3f0e3f6dbe48bf80,0x3f7b3ec4bf55bf35,0x3f55bec4bf7b8000,0x3e48bf6dbf0e3f35,0xbf0ebf6d3e483f80,0xbf7bbec43f553f35,
0x3f27bf18bf6a3e48,0xbe2fbf80be893f62,0x3f1d3f67be60bf80,0x3f803e79bf65bf22,0xbea13f5c3f31bf0e,0x3f093f71bdfbbf7f,0xbf5fbf2c3f133f6d,0xbf6f3e163f7f3e95,
0xbf42bf4e3ecf3f7b,0xbf7cbd493f773ef1,0x3f4abedbbf7a8000,0x3cc9bf78bee63f46,0x3f733f04bf39bf55,0x3f58beacbf7ebdc9,0xbefc3f3e3f51bec4,0x3eb83f7d3d97bf75,
0x3f803e95bf5cbf35,0x3f18bf22bf673e48,0xbeacbf7fbe163f6d,0xbf78bef13f3e3f55,0xbf2cbf623e793f80,0xbf7dbdc93f713f0e,0xbedb3f463f4ebec4,0x3f043f75bd49bf7b,
0x3d49bf75bf043f35,0xbf4ebf463edb3f7b,0xbf713dc93f7d3ec4,0xbe793f623f2cbf0e,0xbf3e3ef13f788000,0x3e163f7f3eacbf55,0x3f673f22bf18bf6d,0x3f5cbe95bf80be48,
0x3f583f3ebee6bf7b,0x3f5fbe79bf80be95,0xbf6a3e163f7e3ec4,0xbd973f713f13bf22,0x3e2fbf67bf273f0e,0xbf4abf4e3eb83f7f,0x3f393f5cbe89bf80,0x3f73bd49bf7abef1,
0x3f09bf2cbf653e48,0xbefcbf78bcc93f75,0x3ecf3f7d3dfbbf6d,0x3f7f3eacbf51bf46,0xbf7cbedb3f423f55,0xbf1d3f183f6fbdc9,0x3f31bf04bf778000,0xbea1bf80be603f62,
0xbf46bf553e953f80,0xbf623e483f7f3ec4,0x3dc93f7b3ef1bf35,0x3f753f0ebf22bf6d,0x3f22bf0ebf750000,0xbef1bf7bbdc93f6d,0xbf7fbe483f623f35,0xbe953f553f46bec4,
0xbf223f0e3f758000,0x3ef13f7b3dc9bf6d,0x3f7f3e48bf62bf35,0x3e95bf55bf463ec4,0xbf46bf553e953f80,0xbf623e483f7f3ec4,0x3dc93f7b3ef1bf35,0x3f753f0ebf22bf6d,
0xbeb8bf80be893f55,0xbf7fbe793f583f46,0x3f513f4ebea1bf80,0x3f4abeacbf80be95,0x3f39bedbbf7ebe48,0xbee6bf7dbe2f3f62,0xbe603f5c3f42bec4,0x3f5f3f3ebecfbf7f,
0xbf6f3d493f773f0e,0x3d973f783f09bf22,0x3f13bf18bf738000,0xbf1dbf713cc93f75,0xbf31bf673dfb3f7b,0xbf653e163f7c3ef1,0x3f7a3f04bf27bf6d,0x3efcbf2cbf6a3dc9,
0xbe79bf7fbedb3f35,0xbf80be953f4e3f55,0xbe163f623f3ebec4,0x3f713f22bf04bf7b,0xbf5cbf463eac3f80,0xbf2c3ef13f7d3e48,0x3f183f753d49bf6d,0x3f67bdc9bf78bf0e,
0xbf78bdc93f673f35,0x3d493f753f18bf0e,0x3f7d3ef1bf2cbf6d,0x3eacbf46bf5c3e48,0xbf043f223f718000,0x3f3e3f62be16bf7b,0x3f4ebe95bf80bec4,0xbedbbf7fbe793f55,
0xbefcbf7dbe603f55,0xbf6a3d493f733f22,0x3f273f713cc9bf6d,0x3f51be79bf7ebef1,0xbf4abf5c3e2f3f7b,0xbf313edb3f7f3e95,0x3f653f3ebeb8bf80,0x3f09bf18bf77bdc9,
0xbf5f3e163f7a3f0e,0x3ecf3f803ea1bf46,0x3f42beacbf80bec4,0xbf13bf78bdfb3f62,0xbf1d3f043f7c3e48,0x3f393f67bd97bf75,0x3ee6bf2cbf6f8000,0xbf58bf4e3e893f7f,
0xbf6dbf353ec43f80,0xbec43f353f6d0000,0x3f6d3f35bec4bf80,0x3ec4bf35bf6d0000,0xbf6dbf353ec43f80,0xbec43f353f6d0000,0x3f6d3f35bec4bf80,0x3ec4bf35bf6d0000,
0xbec43f353f6d8000,0x3f6d3f35bec4bf80,0x3ec4bf35bf6d8000,0xbf6dbf353ec43f80,0xbec43f353f6d8000,0x3f6d3f35bec4bf80,0x3ec4bf35bf6d8000,0xbf6dbf353ec43f80,
0xbf7ebf043f133f7b,0xbcc93f673f42be95,0x3f733f2cbecfbf80,0x3e60bf4ebf5f3dc9,0xbf77be163f583f55,0x3eb83f803ee6bf22,0x3f7f3eacbf39bf6d,0xbe2fbf78bf1d3ef1,
0xbdfb3f5c3f51be48,0x3f803edbbf27bf75,0x3ea1bf3ebf6a8000,0xbf7abf183efc3f7f,0x3e893f7d3f09bf0e,0x3f6f3d49bf65bf46,0xbd97bf71bf313ec4,0xbf7cbe793f4a3f62,
0xbf5c3dc93f713f35,0x3f2c3f753e16bf55,0x3f18bef1bf80bec4,0xbf67bf463e793f7b,0xbf78bf223edb3f80,0xbd493f623f4ebe48,0x3f7d3e95bf3ebf6d,0xbeacbf7fbf043f0e,
0x3f043f7f3eacbf35,0x3f3ebe95bf7dbf0e,0xbf4ebf623d493f6d,0xbedb3f223f783e48,0xbe793f463f678000,0x3f803ef1bf18bf7b,0xbe16bf75bf2c3ec4,0xbf71bdc93f5c3f55,
0x3cc93f673f4abe48,0x3f733e16bf51bf62,0x3f09bf04bf7fbec4,0xbf77bf2c3eb83f7f,0xbf6abd493f5f3f55,0x3f273f783e60bf46,0x3f7c3f18bee6bf80,0xbdfbbf71bf393e95,
0x3f803edbbf1dbf7b,0xbea1bf7dbf133ef1,0xbf58bf5c3d973f6d,0xbe893f3e3f6f3dc9,0x3ecf3f803efcbf0e,0x3f42be79bf7abf22,0x3e2fbf4ebf658000,0xbf7ebeac3f313f75,
0xbf7fbf0e3ef13f80,0x3e953f7b3f22bec4,0x3f46be48bf75bf35,0xbf62bf553dc93f6d,0xbdc93f553f620000,0x3f753e48bf46bf6d,0xbf22bf7bbe953f35,0xbef13f0e3f7f3ec4,
0xbdc93f553f628000,0x3f753e48bf46bf6d,0xbf22bf7bbe953f35,0xbef13f0e3f7f3ec4,0x3f7f3f0ebef1bf80,0xbe95bf7bbf223ec4,0xbf463e483f753f35,0x3f623f55bdc9bf6d,
0xbf133edb3f7f3f0e,0x3f7e3f18becfbf7f,0x3f803f04befcbf80,0xbee6bf80bf093ef1,0x3f7a3f2cbea1bf7b,0xbe89bf78bf313e95,0xbeb8bf7dbf1d3ec4,0xbf273eac3f7c3f22,
0x3f513f673d97bf55,0x3dfbbf4ebf6abdc9,0x3cc9bf5cbf5f8000,0xbf65bd493f583f62,0x3e60bf3ebf73be48,0xbf77be793f393f75,0xbf6fbe163f4a3f6d,0x3f423f713e2fbf46,
0x3f3e3f753e79bf35,0x3e16bf46bf71be48,0xbf67bdc93f4e3f6d,0x3f5c3f623d49bf55,0xbf80bef13f043f80,0x3f183f7f3edbbf0e,0x3eacbf22bf7dbec4,0xbf78be953f2c3f7b,
0x3f2cbe95bf78bf35,0xbf7dbf223eac3f7b,0x3edb3f7f3f18bec4,0x3f04bef1bf80bf0e,0x3d493f623f5c8000,0x3f4ebdc9bf67bf55,0xbf71bf463e163f6d,0x3e793f753f3ebe48,
0x3ee6bf04bf80bf0e,0xbf7abeac3f1d3f7f,0xbf77bf3e3e2f3f6d,0x3ecf3f7d3f27be95,0xbd973f4e3f6f3e48,0x3f51bd49bf5fbf62,0x3f7e3edbbf09bf80,0xbf39bf78bea13f22,
0xbf65bf5cbcc93f55,0x3e603f713f4abdc9,0xbe893f2c3f7c3ec4,0x3f6a3e16bf42bf75,0x3f7f3f18beb8bf7b,0xbf13bf80befc3ef1,0xbdfbbf67bf588000,0xbf313e793f733f46,
0xbf7bbec43f0e3f80,0x3f553f6d3e48bf35,0xbe48bf6dbf550000,0xbf0e3ec43f7b3f35,0x3f7b3ec4bf0ebf80,0xbf55bf6dbe483f35,0x3e483f6d3f550000,0x3f0ebec4bf7bbf35,
0x3e483f6d3f558000,0x3f0ebec4bf7bbf35,0xbf7bbec43f0e3f80,0x3f553f6d3e48bf35,0xbe48bf6dbf558000,0xbf0e3ec43f7b3f35,0x3f7b3ec4bf0ebf80,0xbf55bf6dbe483f35,
0x3ee63f7d3f31be48,0x3e60bf2cbf7ebef1,0x3f773eacbf13bf80,0xbf6abf5cbd973f46,0xbf42bf78beb83f0e,0x3e2f3f673f5f3dc9,0xbf4a3d493f583f6d,0x3f803f18bea1bf75,
0x3f653e16bf39bf7b,0xbf7abf3e3dfb3f62,0xbe89bf71bf518000,0xbecf3f043f7f3f22,0xbf273e793f6f3f55,0x3f7c3edbbefcbf7f,0x3f1d3f803f09bec4,0x3cc9bf4ebf73be95,
0x3edbbef1bf7dbf35,0xbf5cbdc93f3e3f7b,0x3f803f22be79bf6d,0xbf4ebf75beac3f0e,0xbf71be953f183f80,0x3f783f46bd49bf55,0xbf2cbf7fbf043ec4,0x3e163f623f673e48,
0xbf67bf62be163f35,0x3f043f7f3f2cbe48,0x3d49bf46bf78bec4,0xbf183e953f713f55,0x3eac3f753f4e8000,0x3e79bf22bf80bf0e,0xbf3e3dc93f5c3f6d,0x3f7d3ef1bedbbf7b,
0xbf51bd493f423f7b,0x3f7e3f04beb8bf75,0x3cc93f4e3f773ec4,0x3ee6bedbbf7abf46,0x3f583f713ea1bf0e,0xbefcbf7dbf393dc9,0x3f6a3e79bf1dbf80,0xbf7fbf2c3e2f3f62,
0x3f133f803f27be48,0xbdfbbf5cbf6fbe95,0x3f803f18be89bf6d,0xbf65bf67be603f22,0x3f09beacbf73bf55,0xbf5fbe163f313f7f,0xbecfbf78bf4a8000,0xbd973f3e3f7c3ef1,
0xbf62be483f223f80,0x3f7f3f0ebe95bf6d,0xbf75bf55bdc93f35,0x3f463f7b3ef1bec4,0xbef1bf7bbf460000,0x3dc93f553f753ec4,0x3e95bf0ebf7fbf35,0xbf223e483f623f6d,
0x3ef13f7b3f468000,0xbdc9bf55bf75bec4,0xbe953f0e3f7f3f35,0x3f22be48bf62bf6d,0xbf62be483f223f80,0x3f7f3f0ebe95bf6d,0xbf75bf55bdc93f35,0x3f463f7b3ef1bec4,
0x3f803f2cbdfbbf55,0xbf73bf5cbe2f3f22,0x3f583e16bf27bf80,0xbf77bedb3ecf3f75,0x3eb83f713f5f3e48,0xbd97bf4ebf7abef1,0x3f513f783ee6bec4,0xbf1dbf80bf313dc9,
0x3cc9bf3ebf7ebf0e,0xbea13f043f7c3f46,0xbf09bf7dbf428000,0x3e893f673f6a3e95,0x3f6f3eacbefcbf7b,0xbf7fbf183e603f62,0x3f13be79bf65bf6d,0xbf4abd493f393f7f,
0xbf7dbf46bd493f35,0x3f713f623e79bf0e,0xbf5cbf75bedb3ec4,0x3f3e3f7f3f18be48,0xbf4ebdc93f2c3f80,0x3f673e95bf04bf7b,0xbf78bef13eac3f6d,0x3f803f22be16bf55,
0xbe163f223f803f35,0x3eacbef1bf78bf55,0xbf043e953f673f6d,0x3f2cbdc9bf4ebf7b,0x3f183f7f3f3e8000,0xbedbbf75bf5cbe48,0x3e793f623f713ec4,0xbd49bf46bf7dbf0e,
0x3f7e3f18be2fbf55,0xbf80bf2c3d973f46,0x3f733edbbeb8bf6d,0xbf7abf043e893f62,0x3f5f3e79bf09bf7b,0xbf6abeac3ee63f75,0x3f423d49bf31bf80,0xbf51be163f1d3f7f,
0xbdfbbf4ebf7cbf0e,0x3cc93f3e3f7f3f22,0xbea1bf67bf6fbec4,0x3e603f5c3f773ef1,0xbefcbf78bf58be48,0x3ecf3f713f653e95,0xbf27bf80bf398000,0x3f133f7d3f4a3dc9,
0x3f350000bf353f80,0xbf3500003f35bf80,0x3f350000bf353f80,0xbf3500003f35bf80,0x3f350000bf353f80,0xbf3500003f35bf80,0x3f350000bf353f80,0xbf3500003f35bf80,
0xbf353f80bf358000,0x3f35bf803f358000,0xbf353f80bf358000,0x3f35bf803f358000,0xbf353f80bf358000,0x3f35bf803f358000,0xbf353f80bf358000,0x3f35bf803f358000,
0x3f5f3f04bf58bf0e,0x3f6a3edbbf65bef1,0x3f423f2cbf39bf35,0x3f513f18bf4abf22,0x3f7e3e16bf7cbe48,0x3f803d49bf7fbdc9,0x3f733eacbf6fbec4,0x3f7a3e79bf77be95,
0x3efcbf5cbf093f55,0x3ecfbf67bee63f62,0x3f27bf3ebf313f35,0x3f13bf4ebf1d3f46,0x3dfbbf7dbe2f3f7b,0x3cc9bf80bd973f7f,0x3ea1bf71beb83f6d,0x3e60bf78be893f75,
0xbf183f463f2cbf35,0xbedb3f623f04bf55,0xbe793f753eacbf6d,0xbd493f7f3e16bf7b,0xbf7d3dc93f800000,0xbf713e953f78be48,0xbf5c3ef13f67bec4,0xbf3e3f223f4ebf0e,
0x3f4e3f22bf3ebf35,0x3f673ef1bf5cbf0e,0x3f783e95bf71bec4,0x3f803dc9bf7dbe48,0x3e163f7fbd49bf80,0x3eac3f75be79bf7b,0x3f043f62bedbbf6d,0x3f2c3f46bf18bf55,
0xbf6fbedb3f5f3f0e,0xbf7fbe163f7a3e95,0xbf13bf5c3ee63f6d,0xbf4abf2c3f313f46,0xbcc9bf80bdfb3f7b,0xbea1bf783e2f3f7f,0x3f09bf4ebf273f35,0x3e89bf71becf3f62,
0xbeb83f673efcbf55,0xbd973f7d3e60bf75,0xbf513f043f65bec4,0xbf1d3f3e3f39bf22,0xbf80bd493f7e3e48,0xbf733e793f7cbdc9,0xbf58bf183f423f35,0xbf77beac3f6a3ef1,
0x3e953f7bbdc9bf80,0x3f223f55bef1bf6d,0x3f623f0ebf46bf35,0x3f7f3e48bf75bec4,0x3f75be48bf7f0000,0x3f46bf0ebf623ec4,0x3ef1bf55bf223f35,0x3dc9bf7bbe953f6d,
0x3f75be48bf7f8000,0x3f46bf0ebf623ec4,0x3ef1bf55bf223f35,0x3dc9bf7bbe953f6d,0xbe95bf7b3dc93f80,0xbf22bf553ef13f6d,0xbf62bf0e3f463f35,0xbf7fbe483f753ec4,
0xbf583edb3f73be48,0xbefc3f4e3f31bf22,0xbf6abf043f4a3f35,0xbf7fbd493f7c3e95,0x3f513f2cbf27bf55,0x3f7e3e79bf6fbef1,0xbcc93f7d3e89bf6d,0x3ee63f71be60bf7f,
0x3f093f67bea1bf7b,0x3f5f3f18bf39bf46,0xbecf3f5c3f1dbf35,0x3d973f803e2fbf75,0x3f13bf3ebf423f0e,0x3dfbbf78beb83f62,0x3f803e16bf77bec4,0x3f65beacbf7a3dc9,
0xbf71bef13f4e3f35,0xbf783dc93f803e48,0xbf2c3f223f5cbec4,0xbe163f753edbbf55,0x3f67be95bf7d0000,0x3f04bf46bf3e3f0e,0xbd49bf7fbe793f6d,0xbf18bf623eac3f7b,
0xbeac3f623f18bf35,0x3e793f7f3d49bf7b,0x3f3e3f46bf04bf6d,0x3f7d3e95bf67bf0e,0xbedbbf753e163f80,0xbf5cbf223f2c3f55,0xbf80bdc93f783ec4,0xbf4e3ef13f71be48,
0xbf27bf5c3eb83f7b,0xbf7cbeac3f5f3f22,0x3f1dbf2cbf583ec4,0xbcc9bf7dbea13f62,0x3f653f18bf31bf55,0x3f7abd49bf7ebe95,0xbe893f673f13bf35,0x3ecf3f78bd97bf7f,
0xbf423f043f6fbe48,0xbe2f3f713efcbf46,0xbf4abf3e3f093f6d,0xbf80be163f733ef1,0x3ee6bf4ebf393f0e,0xbe60bf80bdfb3f75,0x3f773edbbf51bf35,0x3f6abe79bf7fbdc9,
0xbf0ebf6d3e483f80,0xbf7bbec43f553f35,0xbf553ec43f7b0000,0xbe483f6d3f0ebf35,0x3f0e3f6dbe48bf80,0x3f7b3ec4bf55bf35,0x3f55bec4bf7b0000,0x3e48bf6dbf0e3f35,
0xbf553ec43f7b8000,0xbe483f6d3f0ebf35,0x3f0e3f6dbe48bf80,0x3f7b3ec4bf55bf35,0x3f55bec4bf7b8000,0x3e48bf6dbf0e3f35,0xbf0ebf6d3e483f80,0xbf7bbec43f553f35,
0xbd97bf7dbeb83f55,0xbf51bf3e3efc3f75,0x3f7e3eacbf58bf35,0x3f39bf04bf733dc9,0x3ee63f78bcc9bf7b,0x3f7a3edbbf4abf46,0xbf773d493f7c3ec4,0xbecf3f4e3f42bef1,
0xbf7fbe163f6f3f0e,0xbf133f2c3f5fbe95,0x3dfbbf71bf093f35,0xbf31bf5c3ea13f7f,0x3f65be79bf80be48,0x3e60bf67bf1d3f22,0x3e893f803e2fbf6d,0x3f6a3f18bf27bf62,
0x3d49bf75bf043f35,0xbf4ebf463edb3f7b,0xbf713dc93f7d3ec4,0xbe793f623f2cbf0e,0xbf3e3ef13f780000,0x3e163f7f3eacbf55,0x3f673f22bf18bf6d,0x3f5cbe95bf80be48,
0xbf80be953f5c3f35,0xbf183f223f67be48,0x3eac3f7f3e16bf6d,0x3f783ef1bf3ebf55,0x3f2c3f62be79bf80,0x3f7d3dc9bf71bf0e,0x3edbbf46bf4e3ec4,0xbf04bf753d493f7b,
0xbe60bf80bea13f55,0xbf77bf043f313f62,0x3f6f3f18bf1dbf6d,0x3f42bedbbf7cbdc9,0xbf513eac3f7f3e48,0x3dfb3f7d3ecfbf46,0xbcc9bf78befc3f35,0xbf65bf2c3f093f75,
0xbf7abd493f733f0e,0xbe893f5c3f39bef1,0x3eb8bf4ebf4a3ec4,0xbf27bf673e2f3f7f,0x3f133f71bd97bf7b,0x3f7e3e16bf6abf22,0xbf80be793f5f3f35,0xbee63f3e3f58be95,
0x3f463f55be95bf80,0x3f62be48bf7fbec4,0xbdc9bf7bbef13f35,0xbf75bf0e3f223f6d,0xbf223f0e3f750000,0x3ef13f7b3dc9bf6d,0x3f7f3e48bf62bf35,0x3e95bf55bf463ec4,
0x3f22bf0ebf758000,0xbef1bf7bbdc93f6d,0xbf7fbe483f623f35,0xbe953f553f46bec4,0x3f463f55be95bf80,0x3f62be48bf7fbec4,0xbdc9bf7bbef13f35,0xbf75bf0e3f223f6d,
0x3f6a3f2cbefcbf7b,0x3f27bf04bf7abdc9,0xbf7cbe163f653f35,0xbdfb3f673f31bef1,0xbcc93f713f1dbf0e,0x3f733f18bf13bf75,0xbf09bf78bd973f6d,0xbf77bd493f6f3f22,
0x3ecfbf3ebf5f3e48,0xbf42bf5c3e603f7f,0x3e2f3f7d3ee6bf35,0x3f7e3edbbf39bf62,0x3f803eacbf4abf55,0x3ea1bf4ebf513e95,0xbf583e793f7f3ec4,0x3e893f803eb8bf46,
0x3f783dc9bf67bf35,0xbd49bf75bf183f0e,0xbf7dbef13f2c3f6d,0xbeac3f463f5cbe48,0x3f04bf22bf710000,0xbf3ebf623e163f7b,0xbf4e3e953f803ec4,0x3edb3f7f3e79bf55,
0xbe79bf7fbedb3f35,0xbf80be953f4e3f55,0xbe163f623f3ebec4,0x3f713f22bf04bf7b,0xbf5cbf463eac3f80,0xbf2c3ef13f7d3e48,0x3f183f753d49bf6d,0x3f67bdc9bf78bf0e,
0x3e89bf4ebf583e48,0xbf6fbf2c3ee63f7f,0xbd973f673f39bec4,0x3f7c3f04bf1dbf75,0xbdfbbf78bf133f0e,0xbf80beac3f423f62,0x3ea13f803ecfbf35,0x3f7a3e16bf5fbf46,
0xbf77bf183f093f7b,0xbeb83f3e3f65bdc9,0x3f7f3edbbf31bf6d,0x3e2fbf5cbf4a3e95,0xbf7ebe793f513f55,0x3cc93f713f27bef1,0x3f733d49bf6abf35,0xbe60bf7dbefc3f22,
0xbf6dbf353ec43f80,0xbec43f353f6d0000,0x3f6d3f35bec4bf80,0x3ec4bf35bf6d0000,0xbf6dbf353ec43f80,0xbec43f353f6d0000,0x3f6d3f35bec4bf80,0x3ec4bf35bf6d0000,
0xbec43f353f6d8000,0x3f6d3f35bec4bf80,0x3ec4bf35bf6d8000,0xbf6dbf353ec43f80,0xbec43f353f6d8000,0x3f6d3f35bec4bf80,0x3ec4bf35bf6d8000,0xbf6dbf353ec43f80,
0xbf4a3e793f7c3f0e,0x3f313f713d97bf62,0x3f65bd49bf6fbf35,0xbf09bf7dbe893f46,0xbefc3f183f7a3e48,0x3f6a3f3ebea1bf7f,0x3f27bedbbf80bec4,0xbf51bf5c3dfb3f75,
0x3f1d3f783e2fbf55,0x3f39beacbf7fbef1,0xbee6bf80beb83f35,0xbf583e163f773f22,0x3f5f3f4ebe60bf7b,0x3ecfbf2cbf73bdc9,0xbf42bf673cc93f6d,0xbf133f043f7e3e95,
0x3f043f7f3eacbf35,0x3f3ebe95bf7dbf0e,0xbf4ebf623d493f6d,0xbedb3f223f783e48,0xbe793f463f670000,0x3f803ef1bf18bf7b,0xbe16bf75bf2c3ec4,0xbf71bdc93f5c3f55,
0x3f5cbdc9bf71bf35,0xbf2cbf75be163f55,0xbf183ef13f803ec4,0x3f673f46be79bf7b,0x3f783f22bedbbf80,0x3d49bf62bf4e3e48,0xbf7dbe953f3e3f6d,0x3eac3f7f3f04bf0e,
0x3f31beacbf7ebf0e,0xbf65bf4e3e2f3f75,0xbf7abe793f423f6d,0x3efc3f803ecfbf22,0x3f6f3f3ebe89bf7b,0x3d97bf5cbf583dc9,0xbf13bf7dbea13f35,0xbf1d3edb3f803ef1,
0xbf39bf71bdfb3f55,0xbee63f183f7c3e95,0x3e603f783f27bec4,0x3f5fbd49bf6abf46,0x3eb8bf2cbf77be48,0xbf7fbf043f093f7f,0xbf513e163f733f35,0x3f4a3f673cc9bf62,
0x3f7f3f0ebef1bf80,0xbe95bf7bbf223ec4,0xbf463e483f753f35,0x3f623f55bdc9bf6d,0x3dc9bf55bf620000,0xbf75be483f463f6d,0x3f223f7b3e95bf35,0x3ef1bf0ebf7fbec4,
0x3dc9bf55bf628000,0xbf75be483f463f6d,0x3f223f7b3e95bf35,0x3ef1bf0ebf7fbec4,0xbf7fbf0e3ef13f80,0x3e953f7b3f22bec4,0x3f46be48bf75bf35,0xbf62bf553dc93f6d,
0xbe2fbf71bf423e48,0xbf4a3e163f6f3f46,0xbf393e793f773f35,0x3f733f3ebe60bf75,0xbf583d493f653f55,0x3f5f3f5cbcc9bf62,0x3f6a3f4ebdfbbf6d,0xbd97bf67bf513dc9,
0xbf7cbeac3f273f7b,0x3f1d3f7d3eb8bf22,0x3f313f783e89bf35,0x3ea1bf2cbf7abe95,0x3f093f803ee6bf0e,0x3efcbf04bf80bef1,0x3ecfbf18bf7ebec4,0xbf7fbedb3f133f7f,
0xbf2c3e953f783f35,0x3f7d3f22beacbf7b,0xbedbbf7fbf183ec4,0xbf043ef13f803f0e,0xbd49bf62bf5c0000,0xbf4e3dc93f673f55,0x3f713f46be16bf6d,0xbe79bf75bf3e3e48,
0x3f3e3f753e79bf35,0x3e16bf46bf71be48,0xbf67bdc93f4e3f6d,0x3f5c3f623d49bf55,0xbf80bef13f043f80,0x3f183f7f3edbbf0e,0x3eacbf22bf7dbec4,0xbf78be953f2c3f7b,
0x3f733e79bf31bf7b,0xbf58bf67bdfb3f46,0xbefcbf80bf133ec4,0xbeb83f183f7f3ef1,0xbf423e163f6a3f55,0x3f7c3f2cbe89bf75,0x3f4a3f713e60bf35,0xbcc9bf5cbf65bdc9,
0xbea1bf78bf393e48,0xbf093edb3f7e3f22,0xbf5fbd493f513f6d,0x3f6f3f4ebd97bf62,0x3f273f7d3ecfbf0e,0x3e2fbf3ebf77be95,0x3f1dbeacbf7abf35,0xbf80bf043ee63f7f,
0xbf7bbec43f0e3f80,0x3f553f6d3e48bf35,0xbe48bf6dbf550000,0xbf0e3ec43f7b3f35,0x3f7b3ec4bf0ebf80,0xbf55bf6dbe483f35,0x3e483f6d3f550000,0x3f0ebec4bf7bbf35,
0x3e483f6d3f558000,0x3f0ebec4bf7bbf35,0xbf7bbec43f0e3f80,0x3f553f6d3e48bf35,0xbe48bf6dbf558000,0xbf0e3ec43f7b3f35,0x3f7b3ec4bf0ebf80,0xbf55bf6dbe483f35,
0x3f733f4ebcc9bf55,0xbf09bf80bf1d3e95,0x3efcbedbbf7cbf35,0xbf6fbe793f273f7f,0xbf7fbf043ecf3f7b,0x3f513f713e89bf22,0xbdfb3f3e3f7a3ec4,0x3f39be16bf65bf62,
0x3ea1bf18bf80bf0e,0xbf58bd493f4a3f75,0xbf5fbf67be2f3f35,0x3eb83f783f42bdc9,0x3d973f5c3f6a3e48,0x3f13beacbf77bf46,0x3f7e3f2cbe60bf6d,0xbf31bf7dbee63ef1,
0xbf67bf62be163f35,0x3f043f7f3f2cbe48,0x3d49bf46bf78bec4,0xbf183e953f713f55,0x3eac3f753f4e0000,0x3e79bf22bf80bf0e,0xbf3e3dc93f5c3f6d,0x3f7d3ef1bedbbf7b,
0xbedb3ef13f7d3f35,0x3f5c3dc9bf3ebf7b,0xbf80bf223e793f6d,0x3f4e3f753eacbf0e,0x3f713e95bf18bf80,0xbf78bf463d493f55,0x3f2c3f7f3f04bec4,0xbe16bf62bf67be48,
0x3f7c3f3ebd97bf55,0xbf4abf78becf3ef1,0x3f31be16bf5fbf6d,0xbf73beac3f093f7f,0xbe60bf67bf65be48,0xbe893f183f803f22,0xbf6fbf5cbdfb3f35,0x3f273f803f13be95,
0x3e2fbf2cbf7fbf0e,0xbf1d3e793f6a3f62,0xbf39bf7dbefc3ec4,0x3ea13f713f583dc9,0xbf7abedb3ee63f7b,0x3f773f4e3cc9bf46,0xbeb83f043f7e3f35,0x3f42bd49bf51bf75,
0x3f623e48bf22bf80,0xbf7fbf0e3e953f6d,0x3f753f553dc9bf35,0xbf46bf7bbef13ec4,0x3ef13f7b3f460000,0xbdc9bf55bf75bec4,0xbe953f0e3f7f3f35,0x3f22be48bf62bf6d,
0xbef1bf7bbf468000,0x3dc93f553f753ec4,0x3e95bf0ebf7fbf35,0xbf223e483f623f6d,0x3f623e48bf22bf80,0xbf7fbf0e3e953f6d,0x3f753f553dc9bf35,0xbf46bf7bbef13ec4,
0xbf393d493f4a3f7b,0x3f653e79bf13bf7f,0xbe603f183f7f3f35,0x3efcbeacbf6fbf62,0xbf6abf67be893f0e,0x3f423f7d3f09be95,0xbf7cbf043ea13f6d,0x3f7e3f3ebcc9bf46,
0x3f313f803f1dbe48,0xbee6bf78bf51bdc9,0x3f7a3f4e3d97bf35,0xbf5fbf71beb83ef1,0xbecf3edb3f773f55,0x3f27be16bf58bf75,0x3e2f3f5c3f733ec4,0x3dfbbf2cbf80bf22,
0x3e16bf22bf80bf35,0xbeac3ef13f783f55,0x3f04be95bf67bf6d,0xbf2c3dc93f4e3f7b,0xbf18bf7fbf3e0000,0x3edb3f753f5c3e48,0xbe79bf62bf71bec4,0x3d493f463f7d3f0e,
0xbf7dbf46bd493f35,0x3f713f623e79bf0e,0xbf5cbf75bedb3ec4,0x3f3e3f7f3f18be48,0xbf4ebdc93f2c3f80,0x3f673e95bf04bf7b,0xbf78bef13eac3f6d,0x3f803f22be16bf55,
0x3f4a3f7d3f13be48,0xbf39bf80bf273dc9,0x3f653f713ecfbec4,0xbf58bf78befc3e95,0x3f773f5c3e60bf0e,0xbf6fbf67bea13ef1,0x3f7f3f3e3cc9bf35,0xbf7cbf4ebdfb3f22,
0x3f1dbe16bf51bf7b,0xbf313d493f423f7f,0x3ee6beacbf6abf6d,0xbf093e793f5f3f75,0x3e89bf04bf7abf55,0xbeb83edb3f733f62,0x3d97bf2cbf80bf35,0xbe2f3f183f7e3f46,
0x3f003f003f003f00,0x3f003f003f003f00,0x3f003f003f003f00,0x3f003f003f003f00,0x3f003f003f003f00,0x3f003f003f003f00,0x3f003f003f003f00,0x3f003f003f003f00,
0xbf003f00bf003f00,0xbf003f00bf003f00,0xbf003f00bf003f00,0xbf003f00bf003f00,0xbf003f00bf003f00,0xbf003f00bf003f00,0xbf003f00bf003f00,0xbf003f00bf003f00,
0x3e893e793e603e48,0x3eb83eac3ea13e95,0x3d973d493cc90000,0x3e2f3e163dfb3dc9,0x3f1d3f183f133f0e,0x3f313f2c3f273f22,0x3ee63edb3ecf3ec4,0x3f093f043efc3ef1,
0x3f773f783f7a3f7b,0x3f6f3f713f733f75,0x3f7f3f803f803f80,0x3f7c3f7d3f7e3f7f,0x3f4a3f4e3f513f55,0x3f393f3e3f423f46,0x3f653f673f6a3f6d,0x3f583f5c3f5f3f62,
0xbf18bf22bf2cbf35,0xbedbbef1bf04bf0e,0xbe79be95beacbec4,0xbd49bdc9be16be48,0xbf7dbf7fbf80bf80,0xbf71bf75bf78bf7b,0xbf5cbf62bf67bf6d,0xbf3ebf46bf4ebf55,
0x3f4e3f463f3e3f35,0x3f673f623f5c3f55,0x3f783f753f713f6d,0x3f803f7f3f7d3f7b,0x3e163dc93d498000,0x3eac3e953e793e48,0x3f043ef13edb3ec4,0x3f2c3f223f183f0e,
0xbf6abf71bf77bf7b,0xbf42bf4ebf58bf62,0xbf7cbf78bf73bf6d,0xbf7ebf80bf80bf7f,0xbf39bf2cbf1dbf0e,0xbf65bf5cbf51bf46,0xbe60be16bd970000,0xbefcbedbbeb8be95,
0x3ecf3eac3e893e48,0x3f273f183f093ef1,0xbe2fbe79bea1bec4,0x3dfb3d49bcc9bdc9,0xbf31bf3ebf4abf55,0xbee6bf04bf13bf22,0xbf7abf7dbf7fbf80,0xbf5fbf67bf6fbf75,
0x3f753f7b3f7f3f80,0x3f463f553f623f6d,0x3ef13f0e3f223f35,0x3dc93e483e953ec4,0xbe95be48bdc90000,0xbf22bf0ebef1bec4,0xbf62bf55bf46bf35,0xbf7fbf7bbf75bf6d,
0xbe95be48bdc98000,0xbf22bf0ebef1bec4,0xbf62bf55bf46bf35,0xbf7fbf7bbf75bf6d,0xbf75bf7bbf7fbf80,0xbf46bf55bf62bf6d,0xbef1bf0ebf22bf35,0xbdc9be48be95bec4,
0x3f7a3f713f653f55,0x3f773f7d3f803f7f,0x3eb83e793dfb0000,0x3f423f2c3f133ef1,0xbe2fbd493d973e48,0xbf1dbf04becfbe95,0x3f393f4e3f5f3f6d,0x3ea13edb3f093f22,
0x3e603eac3ee63f0e,0xbe89be16bcc93dc9,0x3f6f3f783f7e3f80,0x3f273f3e3f513f62,0xbf7cbf80bf7fbf7b,0xbf4abf5cbf6abf75,0xbf31bf18befcbec4,0xbf73bf67bf58bf46,
0x3f713f623f4e3f35,0x3f783f7f3f803f7b,0x3f2c3f463f5c3f6d,0x3e163e953edb3f0e,0xbf67bf75bf7dbf80,0xbf04bf22bf3ebf55,0x3d49bdc9be79bec4,0x3f183ef13eac3e48,
0x3eac3ef13f183f35,0xbe79bdc93d493e48,0xbf3ebf22bf04bec4,0xbf7dbf75bf67bf55,0x3edb3e953e168000,0x3f5c3f463f2c3f0e,0x3f803f7f3f783f6d,0x3f4e3f623f713f7b,
0x3f7f3f783f6a3f55,0x3f513f673f773f7f,0x3dfbbd49be60bec4,0x3f393f183ee63e95,0xbf73bf7dbf80bf7b,0xbf09bf2cbf4abf62,0xbefcbeacbe2f0000,0xbf6fbf5cbf42bf22,
0x3d973e793ecf3f0e,0xbf13bedbbe89bdc9,0x3f7e3f803f7a3f6d,0x3f313f4e3f653f75,0x3ea13e16bcc9be48,0x3f583f3e3f1d3ef1,0xbf5fbf71bf7cbf80,0xbeb8bf04bf27bf46,
0x3f553f6d3f7b3f80,0x3e483ec43f0e3f35,0xbf0ebec4be480000,0xbf7bbf6dbf55bf35,0xbf55bf6dbf7bbf80,0xbe48bec4bf0ebf35,0x3f0e3ec43e480000,0x3f7b3f6d3f553f35,
0xbf0ebec4be488000,0xbf7bbf6dbf55bf35,0xbf55bf6dbf7bbf80,0xbe48bec4bf0ebf35,0x3f0e3ec43e488000,0x3f7b3f6d3f553f35,0x3f553f6d3f7b3f80,0x3e483ec43f0e3f35,
0x3f273f4e3f6a3f7b,0xbe2f3d493e893ef1,0x3f1d3edb3e600000,0x3f803f783f653f46,0xbea1bf04bf31bf55,0x3f093eac3dfbbdc9,0xbf5fbf3ebf13bec4,0xbf6fbf7dbf7fbf75,
0xbf42bf18becfbe48,0xbf7cbf80bf77bf62,0x3f4a3f673f7a3f80,0x3cc93e793ee63f22,0x3f733f5c3f393f0e,0x3f583f713f7e3f7f,0xbefcbf2cbf51bf6d,0x3eb83e16bd97be95,
0x3d493e953f043f35,0xbf4ebf22bedbbe48,0xbf71bf7fbf7dbf6d,0xbe79bef1bf2cbf55,0xbf3ebf62bf78bf80,0x3e16bdc9beacbf0e,0x3f673f463f183ec4,0x3f5c3f753f803f7b,
0xbf80bf75bf5cbf35,0xbf18bf46bf67bf7b,0x3eac3dc9be16bec4,0x3f783f623f3e3f0e,0x3f2c3ef13e798000,0x3f7d3f7f3f713f55,0x3edb3f223f4e3f6d,0xbf04be95bd493e48,
0xbf58bf2cbee6be48,0xbf5fbf78bf80bf75,0x3f6a3f7d3f7e3f6d,0x3d973eac3f133f46,0xbe2fbedbbf27bf55,0x3f4a3f183eb83dc9,0xbf39bf04be890000,0xbf73bf80bf7abf62,
0xbf09bf3ebf65bf7b,0x3efc3e79bcc9be95,0xbecfbe163dfb3ec4,0xbf7fbf71bf51bf22,0x3f7c3f673f423f0e,0x3f1d3f4e3f6f3f7f,0xbf31bf5cbf77bf80,0x3ea13d49be60bef1,
0x3f223f553f753f80,0xbef1be483dc93ec4,0xbf7fbf7bbf62bf35,0xbe95bf0ebf46bf6d,0x3f463f0e3e950000,0x3f623f7b3f7f3f6d,0xbdc93e483ef13f35,0xbf75bf55bf22bec4,
0xbf46bf0ebe958000,0xbf62bf7bbf7fbf6d,0x3dc9be48bef1bf35,0x3f753f553f223ec4,0x3f223f553f753f80,0xbef1be483dc93ec4,0xbf7fbf7bbf62bf35,0xbe95bf0ebf46bf6d,
0xbeb8bd493e893f0e,0xbf7fbf78bf58bf22,0x3f513f183ea10000,0x3f4a3f713f803f75,0x3f393f673f7e3f7b,0xbee6be163e2f3ef1,0xbe60bf04bf42bf6d,0x3f5f3f2c3ecf3dc9,
0xbf6fbf80bf77bf55,0x3d97be79bf09bf46,0x3f133f4e3f733f80,0xbf1dbeacbcc93e95,0xbf31bedbbdfb3e48,0xbf65bf7dbf7cbf62,0x3f7a3f5c3f273ec4,0x3efc3f3e3f6a3f7f,
0xbf78bf7fbf67bf35,0x3d49be95bf18bf55,0x3f7d3f623f2c3ec4,0x3eac3f223f5c3f7b,0xbf04bf46bf71bf80,0x3f3e3ef13e16be48,0x3f4e3f753f803f6d,0xbedbbdc93e793f0e,
0x3e79bdc9bedbbf35,0x3f803f753f4e3f0e,0x3e163ef13f3e3f6d,0xbf71bf46bf04be48,0x3f5c3f223eac8000,0x3f2c3f623f7d3f7b,0xbf18be953d493ec4,0xbf67bf7fbf78bf55,
0x3efc3e16be60bf0e,0x3f6a3f803f733f46,0xbf27beac3cc93ec4,0xbf51bf78bf7ebf62,0x3f4a3f043e2fbe48,0x3f313f673f7f3f75,0xbf65bf2cbeb80000,0xbf09bf4ebf77bf7f,
0x3f5f3f7d3f7a3f55,0xbecfbd493ea13f22,0xbf42bf71bf80bf6d,0x3f133e79bdfbbef1,0x3f1d3f5c3f7c3f7b,0xbf39bedbbd973e95,0xbee6bf3ebf6fbf80,0x3f583f183e89bdc9,
0x3ec43f353f6d3f80,0xbf6dbf35bec40000,0xbec4bf35bf6dbf80,0x3f6d3f353ec40000,0x3ec43f353f6d3f80,0xbf6dbf35bec40000,0xbec4bf35bf6dbf80,0x3f6d3f353ec40000,
0xbf6dbf35bec48000,0xbec4bf35bf6dbf80,0x3f6d3f353ec48000,0x3ec43f353f6d3f80,0xbf6dbf35bec48000,0xbec4bf35bf6dbf80,0x3f6d3f353ec48000,0x3ec43f353f6d3f80,
0xbf7ebf5cbf13be48,0xbcc9bedbbf42bf75,0x3f733f3e3ecf0000,0x3e603f183f5f3f7f,0xbf77bf7dbf58bf0e,0x3eb8bd49bee6bf46,0x3f7f3f713f393ec4,0xbe2f3e793f1d3f62,
0xbdfbbf04bf51bf7b,0x3f803f673f273e95,0x3ea13f2c3f6a3f80,0xbf7abf4ebefcbdc9,0x3e89be16bf09bf55,0x3f6f3f803f653f22,0xbd973eac3f313f6d,0xbf7cbf78bf4abef1,
0x3f043dc9beacbf35,0x3f3e3f753f7d3f55,0xbf4ebef1bd493ec4,0xbedbbf46bf78bf7b,0xbe79bf22bf67bf80,0x3f803f623f183e48,0xbe163e953f2c3f6d,0xbf71bf7fbf5cbf0e,
0x3f5c3f7f3f713f35,0xbf2cbe953e163f0e,0xbf18bf62bf80bf6d,0x3f673f223e79be48,0x3f783f463edb8000,0x3d493ef13f4e3f7b,0xbf7dbf75bf3ebec4,0x3eacbdc9bf04bf55,
0xbcc93edb3f4a3f7b,0xbf73bf7dbf51bef1,0xbf09bf5cbf7fbf6d,0x3f773f3e3eb8bdc9,0x3f6a3f803f5f3f0e,0xbf27be793e603f22,0xbf7cbf4ebee60000,0x3dfbbeacbf39bf75,
0xbf80bf67bf1dbe48,0x3ea1be16bf13bf62,0x3f583f043d97bec4,0x3e893f2c3f6f3f7f,0xbecf3d493efc3f55,0xbf42bf78bf7abf46,0xbe2fbf18bf65bf80,0x3f7e3f713f313e95,
0x3dc93f0e3f623f80,0xbf75bf7bbf46bec4,0x3f223e48be95bf35,0x3ef13f553f7f3f6d,0xbf7fbf55bef10000,0x3e95be48bf22bf6d,0x3f463f7b3f753f35,0xbf62bf0ebdc93ec4,
0xbf7fbf55bef18000,0x3e95be48bf22bf6d,0x3f463f7b3f753f35,0xbf62bf0ebdc93ec4,0xbdc9bf0ebf62bf80,0x3f753f7b3f463ec4,0xbf22be483e953f35,0xbef1bf55bf7fbf6d,
0xbf13bf67bf7fbf55,0x3f7e3f4e3ecfbdc9,0x3f803f5c3efc0000,0xbee63d493f093f62,0x3f7a3f3e3ea1be48,0xbe893e793f313f75,0xbeb83e163f1d3f6d,0xbf27bf71bf7cbf46,
0x3f513edbbd97bf0e,0x3dfb3f183f6a3f7f,0x3cc93f043f5f3f80,0xbf65bf80bf58bef1,0x3e603f2c3f733f7b,0xbf77bf78bf39be95,0xbf6fbf7dbf4abec4,0x3f423eacbe2fbf22,
0x3f2c3f753f783f35,0xbf7dbf46beac3e48,0x3edbbdc9bf18bf6d,0x3f043f623f803f55,0x3d49bef1bf5cbf80,0x3f4e3f7f3f673f0e,0xbf71bf22be163ec4,0x3e79be95bf3ebf7b,
0xbf3ebe953e793f35,0xbe16bf22bf71bf7b,0x3f673f7f3f4e3ec4,0xbf5cbef13d493f0e,0x3f803f623f048000,0xbf18bdc93edb3f55,0xbeacbf46bf7dbf6d,0x3f783f753f2c3e48,
0xbee6bf5cbf80bf55,0x3f7a3f713f1d3dc9,0x3f773f2c3e2fbec4,0xbecf3e163f273f75,0x3d973f183f6f3f7b,0xbf51bf80bf5fbef1,0xbf7ebf67bf090000,0x3f393e79bea1bf46,
0x3f653f04bcc9bf0e,0xbe603eac3f4a3f7f,0x3e893f3e3f7c3f6d,0xbf6abf7dbf42be95,0xbf7fbf4ebeb83e48,0x3f133d49befcbf62,0x3dfbbedbbf58bf80,0x3f313f783f733f22,
0xbe483ec43f553f80,0xbf0ebf6dbf7bbf35,0x3f7b3f6d3f0e0000,0xbf55bec43e483f35,0x3e48bec4bf55bf80,0x3f0e3f6d3f7b3f35,0xbf7bbf6dbf0e0000,0x3f553ec4be48bf35,
0xbf7bbf6dbf0e8000,0x3f553ec4be48bf35,0xbe483ec43f553f80,0xbf0ebf6dbf7bbf35,0x3f7b3f6d3f0e8000,0xbf55bec43e483f35,0x3e48bec4bf55bf80,0x3f0e3f6d3f7b3f35,
0x3ee6be16bf31bf7b,0x3e603f3e3f7e3f62,0x3f773f713f130000,0xbf6abf043d973f22,0xbf42be793eb83f55,0x3e2fbedbbf5fbf7f,0xbf4abf80bf58bec4,0x3f803f4e3ea1be95,
0x3f653f7d3f393e48,0xbf7abf2cbdfb3ef1,0xbe893eac3f513f80,0xbecfbf5cbf7fbf46,0xbf27bf78bf6fbf0e,0x3f7c3f673efcbdc9,0x3f1d3d49bf09bf6d,0x3cc93f183f733f75,
0xbf67bef13e163f35,0x3f04bdc9bf2cbf7b,0x3d493f223f783f6d,0xbf18bf75bf71bf0e,0x3eacbe95bf4ebf80,0x3e793f463f803f55,0xbf3ebf7fbf5cbec4,0x3f7d3f623edbbe48,
0xbedbbf62bf7dbf35,0x3f5c3f7f3f3e3e48,0xbf80bf46be793ec4,0x3f4e3e95beacbf55,0x3f713f753f188000,0xbf78bf22bd493f0e,0x3f2c3dc9bf04bf6d,0xbe163ef13f673f7b,
0x3f513f803f423e48,0xbf7ebf5cbeb83e95,0xbcc93f183f773f6d,0xbee6bf67bf7abf22,0xbf58beac3ea13f55,0x3efcbe16bf39bf7f,0xbf6abf78bf1d0000,0x3f7f3f3e3e2fbef1,
0xbf133d493f273f7b,0x3dfbbf04bf6fbf75,0xbf80bf4ebe893ec4,0x3f653edbbe60bf46,0xbf09bf71bf73bf0e,0x3f5f3f7d3f313dc9,0x3ecfbe79bf4abf80,0x3d973f2c3f7c3f62,
0xbef13e483f463f80,0x3dc9bf0ebf75bf6d,0x3e953f553f7f3f35,0xbf22bf7bbf62bec4,0x3f623f7b3f220000,0xbf7fbf55be953ec4,0x3f753f0ebdc9bf35,0xbf46be483ef13f6d,
0xbf62bf7bbf228000,0x3f7f3f553e95bec4,0xbf75bf0e3dc93f35,0x3f463e48bef1bf6d,0xbef13e483f463f80,0x3dc9bf0ebf75bf6d,0x3e953f553f7f3f35,0xbf22bf7bbf62bec4,
0x3f803f3e3dfbbf0e,0xbf73bf043e2f3f46,0x3f583f7d3f270000,0xbf77bf67becf3e95,0x3eb8beacbf5fbf7b,0xbd973f183f7a3f62,0x3f513e79bee6bf6d,0xbf1d3d493f313f7f,
0x3cc93f2c3f7e3f55,0xbea1bf5cbf7cbf22,0xbf093e163f423f80,0x3e89bedbbf6abf75,0x3f6f3f713efcbe48,0xbf7fbf4ebe603ef1,0x3f133f783f653ec4,0xbf4abf80bf39bdc9,
0xbe16bf46bf80bf35,0x3eac3f623f783f0e,0xbf04bf75bf67bec4,0x3f2c3f7f3f4e3e48,0x3f18bdc9bf3ebf80,0xbedb3e953f5c3f7b,0x3e79bef1bf71bf6d,0xbd493f223f7d3f55,
0x3f7d3f22bd49bf35,0xbf71bef13e793f55,0x3f5c3e95bedbbf6d,0xbf3ebdc93f183f7b,0x3f4e3f7f3f2c8000,0xbf67bf75bf043e48,0x3f783f623eacbec4,0xbf80bf46be163f0e,
0xbf7ebf4ebe2f3f0e,0x3f803f3e3d97bf22,0xbf73bf67beb83ec4,0x3f7a3f5c3e89bef1,0xbf5fbf78bf093e48,0x3f6a3f713ee6be95,0xbf42bf80bf310000,0x3f513f7d3f1dbdc9,
0x3dfbbf18bf7cbf55,0xbcc93f2c3f7f3f46,0x3ea1bedbbf6fbf6d,0xbe603f043f773f62,0x3efcbe79bf58bf7b,0xbecf3eac3f653f75,0x3f27bd49bf39bf80,0xbf133e163f4a3f7f,
0x3f003f003f003f00,0x3f003f003f003f00,0x3f003f003f003f00,0x3f003f003f003f00,0x3f003f003f003f00,0x3f003f003f003f00,0x3f003f003f003f00,0x3f003f003f003f00,
0xbf003f00bf003f00,0xbf003f00bf003f00,0xbf003f00bf003f00,0xbf003f00bf003f00,0xbf003f00bf003f00,0xbf003f00bf003f00,0xbf003f00bf003f00,0xbf003f00bf003f00,
0x3f5f3f5c3f583f55,0x3f6a3f673f653f62,0x3f423f3e3f393f35,0x3f513f4e3f4a3f46,0x3f7e3f7d3f7c3f7b,0x3f803f803f7f3f7f,0x3f733f713f6f3f6d,0x3f7a3f783f773f75,
0x3efc3f043f093f0e,0x3ecf3edb3ee63ef1,0x3f273f2c3f313f35,0x3f133f183f1d3f22,0x3dfb3e163e2f3e48,0x3cc93d493d973dc9,0x3ea13eac3eb83ec4,0x3e603e793e893e95,
0x3f4e3f463f3e3f35,0x3f673f623f5c3f55,0x3f783f753f713f6d,0x3f803f7f3f7d3f7b,0x3e163dc93d490000,0x3eac3e953e793e48,0x3f043ef13edb3ec4,0x3f2c3f223f183f0e,
0x3f183f223f2c3f35,0x3edb3ef13f043f0e,0x3e793e953eac3ec4,0x3d493dc93e163e48,0x3f7d3f7f3f803f80,0x3f713f753f783f7b,0x3f5c3f623f673f6d,0x3f3e3f463f4e3f55,
0x3f6f3f673f5f3f55,0x3f7f3f7d3f7a3f75,0x3f133f043ee63ec4,0x3f4a3f3e3f313f22,0x3cc9bd49bdfbbe48,0x3ea13e793e2f3dc9,0xbf09bf18bf27bf35,0xbe89beacbecfbef1,
0x3eb83edb3efc3f0e,0x3d973e163e603e95,0x3f513f5c3f653f6d,0x3f1d3f2c3f393f46,0x3f803f803f7e3f7b,0x3f733f783f7c3f7f,0x3f583f4e3f423f35,0x3f773f713f6a3f62,
0xbf75bf7bbf7fbf80,0xbf46bf55bf62bf6d,0xbef1bf0ebf22bf35,0xbdc9be48be95bec4,0x3e953e483dc90000,0x3f223f0e3ef13ec4,0x3f623f553f463f35,0x3f7f3f7b3f753f6d,
0x3e953e483dc98000,0x3f223f0e3ef13ec4,0x3f623f553f463f35,0x3f7f3f7b3f753f6d,0x3f753f7b3f7f3f80,0x3f463f553f623f6d,0x3ef13f0e3f223f35,0x3dc93e483e953ec4,
0xbf58bf67bf73bf7b,0xbefcbf18bf31bf46,0xbf6abf5cbf4abf35,0xbf7fbf80bf7cbf75,0x3f513f3e3f273f0e,0x3f7e3f783f6f3f62,0xbcc9be16be89bec4,0x3ee63eac3e603dc9,
0x3f093edb3ea13e48,0x3f5f3f4e3f393f22,0xbecfbf04bf1dbf35,0x3d97bd49be2fbe95,0x3f133f2c3f423f55,0x3dfb3e793eb83ef1,0x3f803f7d3f773f6d,0x3f653f713f7a3f7f,
0xbeacbef1bf18bf35,0x3e793dc9bd49be48,0x3f3e3f223f043ec4,0x3f7d3f753f673f55,0xbedbbe95be160000,0xbf5cbf46bf2cbf0e,0xbf80bf7fbf78bf6d,0xbf4ebf62bf71bf7b,
0x3f713f623f4e3f35,0x3f783f7f3f803f7b,0x3f2c3f463f5c3f6d,0x3e163e953edb3f0e,0xbf67bf75bf7dbf80,0xbf04bf22bf3ebf55,0x3d49bdc9be79bec4,0x3f183ef13eac3e48,
0x3f273f043eb83e48,0x3f7c3f713f5f3f46,0xbf1dbf3ebf58bf6d,0x3cc9be16bea1bef1,0xbf65bf4ebf31bf0e,0xbf7abf80bf7ebf75,0x3e893edb3f133f35,0xbecfbe79bd973dc9,
0x3f423f5c3f6f3f7b,0x3e2f3eac3efc3f22,0x3f4a3f2c3f093ec4,0x3f803f7d3f733f62,0xbee6bf18bf39bf55,0x3e603d49bdfbbe95,0xbf77bf67bf51bf35,0xbf6abf78bf7fbf7f,
0x3f553f6d3f7b3f80,0x3e483ec43f0e3f35,0xbf0ebec4be480000,0xbf7bbf6dbf55bf35,0xbf55bf6dbf7bbf80,0xbe48bec4bf0ebf35,0x3f0e3ec43e480000,0x3f7b3f6d3f553f35,
0xbf0ebec4be488000,0xbf7bbf6dbf55bf35,0xbf55bf6dbf7bbf80,0xbe48bec4bf0ebf35,0x3f0e3ec43e488000,0x3f7b3f6d3f553f35,0x3f553f6d3f7b3f80,0x3e483ec43f0e3f35,
0xbd973e163eb83f0e,0xbf51bf2cbefcbe95,0x3f7e3f713f583f35,0x3f393f5c3f733f7f,0x3ee63e793cc9be48,0x3f7a3f673f4a3f22,0xbf77bf80bf7cbf6d,0xbecfbf18bf42bf62,
0xbf7fbf7dbf6fbf55,0xbf13bf3ebf5fbf75,0x3dfb3eac3f093f35,0xbf31bf04bea1bdc9,0x3f653f783f803f7b,0x3e603edb3f1d3f46,0x3e893d49be2fbec4,0x3f6a3f4e3f273ef1,
0xbf80bf75bf5cbf35,0xbf18bf46bf67bf7b,0x3eac3dc9be16bec4,0x3f783f623f3e3f0e,0x3f2c3ef13e790000,0x3f7d3f7f3f713f55,0x3edb3f223f4e3f6d,0xbf04be95bd493e48,
0xbd49be95bf04bf35,0x3f4e3f223edb3e48,0x3f713f7f3f7d3f6d,0x3e793ef13f2c3f55,0x3f3e3f623f783f80,0xbe163dc93eac3f0e,0xbf67bf46bf18bec4,0xbf5cbf75bf80bf7b,
0x3e60bd49bea1bf0e,0x3f773f5c3f313ef1,0xbf6fbf4ebf1dbec4,0xbf42bf67bf7cbf7f,0x3f513f713f7f3f7b,0xbdfb3e163ecf3f22,0x3cc9be79befcbf35,0x3f653f3e3f093e95,
0x3f7a3f803f733f55,0x3e893f043f393f62,0xbeb8bf18bf4abf6d,0x3f273edb3e2fbdc9,0xbf13beacbd973e48,0xbf7ebf7dbf6abf46,0x3f803f783f5f3f35,0x3ee63f2c3f583f75,
0xbf22bf55bf75bf80,0x3ef13e48bdc9bec4,0x3f7f3f7b3f623f35,0x3e953f0e3f463f6d,0xbf46bf0ebe950000,0xbf62bf7bbf7fbf6d,0x3dc9be48bef1bf35,0x3f753f553f223ec4,
0x3f463f0e3e958000,0x3f623f7b3f7f3f6d,0xbdc93e483ef13f35,0xbf75bf55bf22bec4,0xbf22bf55bf75bf80,0x3ef13e48bdc9bec4,0x3f7f3f7b3f623f35,0x3e953f0e3f463f6d,
0x3f6a3f3e3efc3e48,0x3f273f5c3f7a3f7f,0xbf7cbf7dbf65bf35,0xbdfbbedbbf31bf62,0xbcc9beacbf1dbf55,0x3f733f4e3f133e95,0xbf09be793d973ec4,0xbf77bf80bf6fbf46,
0x3ecf3f2c3f5f3f7b,0xbf42bf04be603dc9,0x3e2fbe16bee6bf35,0x3f7e3f673f393ef1,0x3f803f713f4a3f0e,0x3ea13f183f513f75,0xbf58bf78bf7fbf6d,0x3e89bd49beb8bf22,
0xbe793dc93edb3f35,0xbf80bf75bf4ebf0e,0xbe16bef1bf3ebf6d,0x3f713f463f043e48,0xbf5cbf22beac0000,0xbf2cbf62bf7dbf7b,0x3f183e95bd49bec4,0x3f673f7f3f783f55,
0xbf78bf7fbf67bf35,0x3d49be95bf18bf55,0x3f7d3f623f2c3ec4,0x3eac3f223f5c3f7b,0xbf04bf46bf71bf80,0x3f3e3ef13e16be48,0x3f4e3f753f803f6d,0xbedbbdc93e793f0e,
0xbe89bf18bf58bf7b,0x3f6f3f3e3ee63dc9,0x3d973edb3f393f6d,0xbf7cbf5cbf1dbe95,0x3dfbbe79bf13bf55,0x3f803f713f423ef1,0xbea13d493ecf3f35,0xbf7abf7dbf5fbf22,
0x3f773f4e3f093e48,0x3eb83f2c3f653f7f,0xbf7fbf67bf31bec4,0xbe2fbf04bf4abf75,0x3f7e3f783f513f0e,0xbcc93eac3f273f62,0xbf73bf80bf6abf35,0x3e60be16befcbf46,
0x3ec43f353f6d3f80,0xbf6dbf35bec40000,0xbec4bf35bf6dbf80,0x3f6d3f353ec40000,0x3ec43f353f6d3f80,0xbf6dbf35bec40000,0xbec4bf35bf6dbf80,0x3f6d3f353ec40000,
0xbf6dbf35bec48000,0xbec4bf35bf6dbf80,0x3f6d3f353ec48000,0x3ec43f353f6d3f80,0xbf6dbf35bec48000,0xbec4bf35bf6dbf80,0x3f6d3f353ec48000,0x3ec43f353f6d3f80,
0xbf4abf78bf7cbf55,0x3f313eacbd97bef1,0x3f653f803f6f3f35,0xbf09be163e893f22,0xbefcbf4ebf7abf7b,0x3f6a3f2c3ea1bdc9,0x3f273f673f803f6d,0xbf51bf04bdfb3e95,
0x3f1d3e79be2fbf0e,0x3f393f713f7f3f62,0xbee6bd493eb83f35,0xbf58bf7dbf77bf46,0x3f5f3f183e60be48,0x3ecf3f3e3f733f7f,0xbf42bedbbcc93ec4,0xbf13bf5cbf7ebf75,
0x3f5c3f7f3f713f35,0xbf2cbe953e163f0e,0xbf18bf62bf80bf6d,0x3f673f223e79be48,0x3f783f463edb0000,0x3d493ef13f4e3f7b,0xbf7dbf75bf3ebec4,0x3eacbdc9bf04bf55,
0xbf04bdc93eac3f35,0xbf3ebf75bf7dbf55,0x3f4e3ef13d49bec4,0x3edb3f463f783f7b,0x3e793f223f673f80,0xbf80bf62bf18be48,0x3e16be95bf2cbf6d,0x3f713f7f3f5c3f0e,
0xbf31bf71bf7ebf55,0x3f653f183e2fbe95,0x3f7a3f783f423ec4,0xbefcbd493ecf3f46,0xbf6fbf2cbe893e48,0xbd97bf04bf58bf7f,0x3f133e16bea1bf35,0x3f1d3f673f803f62,
0x3f393eacbdfbbf0e,0x3ee63f4e3f7c3f75,0xbe603e793f273f6d,0xbf5fbf80bf6abf22,0xbeb8bf3ebf77bf7b,0x3f7f3f5c3f093dc9,0x3f513f7d3f733f35,0xbf4abedb3cc93ef1,
0xbdc9bf0ebf62bf80,0x3f753f7b3f463ec4,0xbf22be483e953f35,0xbef1bf55bf7fbf6d,0x3f7f3f553ef10000,0xbe953e483f223f6d,0xbf46bf7bbf75bf35,0x3f623f0e3dc9bec4,
0x3f7f3f553ef18000,0xbe953e483f223f6d,0xbf46bf7bbf75bf35,0x3f623f0e3dc9bec4,0x3dc93f0e3f623f80,0xbf75bf7bbf46bec4,0x3f223e48be95bf35,0x3ef13f553f7f3f6d,
0xbe2f3eac3f423f7b,0xbf4abf7dbf6fbf22,0xbf39bf78bf77bf35,0x3f733f2c3e60be95,0xbf58bf80bf65bf0e,0x3f5f3f043cc9bef1,0x3f6a3f183dfbbec4,0xbd973edb3f513f7f,
0xbf7cbf71bf27be48,0x3f1d3e16beb8bf46,0x3f313e79be89bf35,0x3ea13f3e3f7a3f75,0x3f093d49bee6bf55,0x3efc3f5c3f803f62,0x3ecf3f4e3f7e3f6d,0xbf7fbf67bf13bdc9,
0x3f3e3e95be79bf35,0x3e163f223f713f7b,0xbf67bf7fbf4ebec4,0x3f5c3ef1bd49bf0e,0xbf80bf62bf040000,0x3f183dc9bedbbf55,0x3eac3f463f7d3f6d,0xbf78bf75bf2cbe48,
0x3f2c3f753f783f35,0xbf7dbf46beac3e48,0x3edbbdc9bf18bf6d,0x3f043f623f803f55,0x3d49bef1bf5cbf80,0x3f4e3f7f3f673f0e,0xbf71bf22be163ec4,0x3e79be95bf3ebf7b,
0xbf73bf78bf31be48,0x3f583edbbdfbbf22,0x3efcbd49bf13bf6d,0x3eb83f4e3f7f3f62,0x3f423f7d3f6a3f0e,0xbf7cbf3ebe893e95,0xbf4abeac3e603f35,0x3cc9bf04bf65bf7f,
0x3ea1be79bf39bf7b,0x3f093f673f7e3f46,0x3f5f3f803f513ec4,0xbf6fbf18bd973ef1,0xbf27be163ecf3f55,0xbe2fbf2cbf77bf75,0xbf1dbf71bf7abf35,0x3f803f5c3ee6bdc9,
0xbe483ec43f553f80,0xbf0ebf6dbf7bbf35,0x3f7b3f6d3f0e0000,0xbf55bec43e483f35,0x3e48bec4bf55bf80,0x3f0e3f6d3f7b3f35,0xbf7bbf6dbf0e0000,0x3f553ec4be48bf35,
0xbf7bbf6dbf0e8000,0x3f553ec4be48bf35,0xbe483ec43f553f80,0xbf0ebf6dbf7bbf35,0x3f7b3f6d3f0e8000,0xbf55bec43e483f35,0x3e48bec4bf55bf80,0x3f0e3f6d3f7b3f35,
0x3f733f183cc9bf0e,0xbf093d493f1d3f75,0x3efc3f673f7c3f35,0xbf6fbf78bf27bdc9,0xbf7fbf5cbecf3e48,0x3f513eacbe89bf46,0xbdfbbf2cbf7abf6d,0x3f393f7d3f653ef1,
0x3ea13f4e3f803f55,0xbf58bf80bf4abe95,0xbf5fbedb3e2f3f35,0x3eb8be79bf42bf7f,0x3d97bf04bf6abf7b,0x3f133f713f773f22,0x3f7e3f3e3e60bec4,0xbf31be163ee63f62,
0xbedbbf62bf7dbf35,0x3f5c3f7f3f3e3e48,0xbf80bf46be793ec4,0x3f4e3e95beacbf55,0x3f713f753f180000,0xbf78bf22bd493f0e,0x3f2c3dc9bf04bf6d,0xbe163ef13f673f7b,
0x3f673ef1be16bf35,0xbf043dc93f2c3f7b,0xbd49bf22bf78bf6d,0x3f183f753f713f0e,0xbeac3e953f4e3f80,0xbe79bf46bf80bf55,0x3f3e3f7f3f5c3ec4,0xbf7dbf62bedb3e48,
0xbf7cbf2cbd973f0e,0x3f4a3e79becfbf62,0xbf31bf7dbf5fbec4,0x3f733f713f09bdc9,0x3e60bedbbf65bf7b,0x3e893f4e3f803f46,0x3f6f3f04bdfbbf35,0xbf27bd493f133f75,
0xbe2fbf3ebf7fbf55,0x3f1d3f783f6a3ef1,0x3f393e16befcbf6d,0xbea13eac3f583f7f,0x3f7a3f673ee6be48,0xbf77bf183cc93f22,0x3eb83f5c3f7e3f35,0xbf42bf80bf51be95,
0x3ef1be48bf46bf80,0xbdc93f0e3f753f6d,0xbe95bf55bf7fbf35,0x3f223f7b3f623ec4,0xbf62bf7bbf220000,0x3f7f3f553e95bec4,0xbf75bf0e3dc93f35,0x3f463e48bef1bf6d,
0x3f623f7b3f228000,0xbf7fbf55be953ec4,0x3f753f0ebdc9bf35,0xbf46be483ef13f6d,0x3ef1be48bf46bf80,0xbdc93f0e3f753f6d,0xbe95bf55bf7fbf35,0x3f223f7b3f623ec4,
0xbf39bf80bf4abe48,0x3f653f783f13bdc9,0xbe60bf4ebf7fbf35,0x3efc3f713f6f3ef1,0xbf6abedb3e893f55,0x3f423e16bf09bf75,0xbf7cbf5cbea13ec4,0x3f7e3f2c3cc9bf22,
0x3f313d49bf1dbf7b,0xbee63e793f513f7f,0x3f7a3f18bd97bf35,0xbf5fbeac3eb83f62,0xbecfbf67bf77bf0e,0x3f273f7d3f583e95,0x3e2fbf04bf73bf6d,0x3dfb3f3e3f803f46,
0xbf7dbf223d493f35,0x3f713ef1be79bf55,0xbf5cbe953edb3f6d,0x3f3e3dc9bf18bf7b,0xbf4ebf7fbf2c0000,0x3f673f753f04be48,0xbf78bf62beac3ec4,0x3f803f463e16bf0e,
0xbe16bf46bf80bf35,0x3eac3f623f783f0e,0xbf04bf75bf67bec4,0x3f2c3f7f3f4e3e48,0x3f18bdc9bf3ebf80,0xbedb3e953f5c3f7b,0x3e79bef1bf71bf6d,0xbd493f223f7d3f55,
0xbf4abe163f133f7b,0x3f393d49bf27bf7f,0xbf65beac3ecf3f6d,0x3f583e79befcbf75,0xbf77bf043e603f55,0x3f6f3edbbea1bf62,0xbf7fbf2c3cc93f35,0x3f7c3f18bdfbbf46,
0xbf1dbf7dbf51be48,0x3f313f803f423dc9,0xbee6bf71bf6abec4,0x3f093f783f5f3e95,0xbe89bf5cbf7abf0e,0x3eb83f673f733ef1,0xbd97bf3ebf80bf35,0x3e2f3f4e3f7e3f22,
0xbf8000003f80,0xbf8000003f80,0xbf8000003f80,0xbf8000003f80,0xbf8000003f80,0xbf8000003f80,0xbf8000003f80,0xbf8000003f80,
0x3f808000bf808000,0x3f808000bf808000,0x3f808000bf808000,0x3f808000bf808000,0x3f808000bf808000,0x3f808000bf808000,0x3f808000bf808000,0x3f808000bf808000,
0xbf77be793f7a3e48,0xbf6fbeac3f733e95,0xbf7fbd493f800000,0xbf7cbe163f7e3dc9,0xbf4abf183f513f0e,0xbf39bf2c3f423f22,0xbf65bedb3f6a3ec4,0xbf58bf043f5f3ef1,
0x3e89bf78be603f7b,0x3eb8bf71bea13f75,0x3d97bf80bcc93f80,0x3e2fbf7dbdfb3f7f,0x3f1dbf4ebf133f55,0x3f31bf3ebf273f46,0x3ee6bf67becf3f6d,0x3f09bf5cbefc3f62,
0xbf4e3f223f3ebf35,0xbf673ef13f5cbf0e,0xbf783e953f71bec4,0xbf803dc93f7dbe48,0xbe163f7f3d49bf80,0xbeac3f753e79bf7b,0xbf043f623edbbf6d,0xbf2c3f463f18bf55,
0xbf18bf463f2c3f35,0xbedbbf623f043f55,0xbe79bf753eac3f6d,0xbd49bf7f3e163f7b,0xbf7dbdc93f808000,0xbf71be953f783e48,0xbf5cbef13f673ec4,0xbf3ebf223f4e3f0e,
0xbecf3f713e89bf7b,0xbf273f4e3f09bf62,0x3e2f3f78bea1bf6d,0xbdfb3f80bcc9bf7f,0x3f313f2cbf4abf0e,0x3ee63f5cbf13bf46,0x3f7a3e16bf7f0000,0x3f5f3edbbf6fbe95,
0xbf6abeac3f773e48,0xbf42bf183f583ef1,0xbf7c3e793f73bec4,0xbf7ebd493f80bdc9,0xbf393f3e3f1dbf55,0xbf653f043f51bf22,0xbe603f7d3d97bf80,0xbefc3f673eb8bf75,
0x3e95bf7bbdc93f80,0x3f22bf55bef13f6d,0x3f62bf0ebf463f35,0x3f7fbe48bf753ec4,0x3f753e48bf7f0000,0x3f463f0ebf62bec4,0x3ef13f55bf22bf35,0x3dc93f7bbe95bf6d,
0x3f753e48bf7f8000,0x3f463f0ebf62bec4,0x3ef13f55bf22bf35,0x3dc93f7bbe95bf6d,0xbe953f7b3dc9bf80,0xbf223f553ef1bf6d,0xbf623f0e3f46bf35,0xbf7f3e483f75bec4,
0xbe60bf713ee63f55,0x3e89bf7dbcc93f7f,0xbf6fbe793f7e0000,0xbf27bf2c3f513ef1,0x3f7c3d49bf7f3e48,0x3f4a3f04bf6abe95,0x3f31bf4ebefc3f6d,0x3f73bedbbf583f22,
0x3f7abeacbf653f0e,0x3f773e16bf803dc9,0x3eb8bf78bdfb3f80,0x3f42bf3ebf133f62,0xbe2f3f80bd97bf7b,0xbf1d3f5c3ecfbf75,0x3f393f18bf5fbec4,0x3ea13f67bf09bf46,
0xbeacbf623f183f35,0x3e79bf7f3d493f7b,0x3f3ebf46bf043f6d,0x3f7dbe95bf673f0e,0xbedb3f753e16bf80,0xbf5c3f223f2cbf55,0xbf803dc93f78bec4,0xbf4ebef13f713e48,
0x3f71bef1bf4e3f35,0x3f783dc9bf803e48,0x3f2c3f22bf5cbec4,0x3e163f75bedbbf55,0xbf67be953f7d8000,0xbf04bf463f3e3f0e,0x3d49bf7f3e793f6d,0x3f18bf62beac3f7b,
0xbd97bf783ecf3f55,0x3f13bf67be893f7f,0xbf7e3d493f7abec4,0xbf31bf183f653e95,0xbea13f7dbcc9bf7b,0xbf583f2c3f1dbf62,0x3f5f3eacbf7c0000,0x3eb83f5cbf27bf22,
0x3f7fbe79bf6a3f0e,0x3f513edbbf77bdc9,0x3dfbbf803e603f6d,0x3f39bf4ebee63f75,0xbf73be163f80be48,0xbf09bf3e3f4a3ef1,0xbefc3f713e2fbf80,0xbf6f3f043f42bf46,
0x3f0ebf6dbe483f80,0x3f7bbec4bf553f35,0x3f553ec4bf7b0000,0x3e483f6dbf0ebf35,0xbf0e3f6d3e48bf80,0xbf7b3ec43f55bf35,0xbf55bec43f7b0000,0xbe48bf6d3f0e3f35,
0x3f553ec4bf7b8000,0x3e483f6dbf0ebf35,0xbf0e3f6d3e48bf80,0xbf7b3ec43f55bf35,0xbf55bec43f7b8000,0xbe48bf6d3f0e3f35,0x3f0ebf6dbe483f80,0x3f7bbec4bf553f35,
0x3f42bf4ebecf3f7b,0x3f7cbd49bf773ef1,0xbf4abedb3f7a0000,0xbcc9bf783ee63f46,0xbf733f043f39bf55,0xbf58beac3f7ebdc9,0x3efc3f3ebf51bec4,0xbeb83f7dbd97bf75,
0x3f273f18bf6abe48,0xbe2f3f80be89bf62,0x3f1dbf67be603f80,0x3f80be79bf653f22,0xbea1bf5c3f313f0e,0x3f09bf71bdfb3f7f,0xbf5f3f2c3f13bf6d,0xbf6fbe163f7fbe95,
0x3f80be95bf5c3f35,0x3f183f22bf67be48,0xbeac3f7fbe16bf6d,0xbf783ef13f3ebf55,0xbf2c3f623e79bf80,0xbf7d3dc93f71bf0e,0xbedbbf463f4e3ec4,0x3f04bf75bd493f7b,
0x3d493f75bf04bf35,0xbf4e3f463edbbf7b,0xbf71bdc93f7dbec4,0xbe79bf623f2c3f0e,0xbf3ebef13f788000,0x3e16bf7f3eac3f55,0x3f67bf22bf183f6d,0x3f5c3e95bf803e48,
0x3f093f2cbf65be48,0xbefc3f78bcc9bf75,0x3ecfbf7d3dfb3f6d,0x3f7fbeacbf513f46,0xbf7c3edb3f42bf55,0xbf1dbf183f6f3dc9,0x3f313f04bf770000,0xbea13f80be60bf62,
0xbf583f3e3ee6bf7b,0xbf5fbe793f80be95,0x3f6a3e16bf7e3ec4,0x3d973f71bf13bf22,0xbe2fbf673f273f0e,0x3f4abf4ebeb83f7f,0xbf393f5c3e89bf80,0xbf73bd493f7abef1,
0x3f46bf55be953f80,0x3f623e48bf7f3ec4,0xbdc93f7bbef1bf35,0xbf753f0e3f22bf6d,0xbf22bf0e3f750000,0x3ef1bf7b3dc93f6d,0x3f7fbe48bf623f35,0x3e953f55bf46bec4,
0x3f223f0ebf758000,0xbef13f7bbdc9bf6d,0xbf7f3e483f62bf35,0xbe95bf553f463ec4,0x3f46bf55be953f80,0x3f623e48bf7f3ec4,0xbdc93f7bbef1bf35,0xbf753f0e3f22bf6d,
0x3f6f3d49bf773f0e,0xbd973f78bf09bf22,0xbf13bf183f730000,0x3f1dbf71bcc93f75,0x3f31bf67bdfb3f7b,0x3f653e16bf7c3ef1,0xbf7a3f043f27bf6d,0xbefcbf2c3f6a3dc9,
0xbeb83f80be89bf55,0xbf7f3e793f58bf46,0x3f51bf4ebea13f80,0x3f4a3eacbf803e95,0x3f393edbbf7e3e48,0xbee63f7dbe2fbf62,0xbe60bf5c3f423ec4,0x3f5fbf3ebecf3f7f,
0xbe793f7fbedbbf35,0xbf803e953f4ebf55,0xbe16bf623f3e3ec4,0x3f71bf22bf043f7b,0xbf5c3f463eacbf80,0xbf2cbef13f7dbe48,0x3f18bf753d493f6d,0x3f673dc9bf783f0e,
0xbf783dc93f67bf35,0x3d49bf753f183f0e,0x3f7dbef1bf2c3f6d,0x3eac3f46bf5cbe48,0xbf04bf223f718000,0x3f3ebf62be163f7b,0x3f4e3e95bf803ec4,0xbedb3f7fbe79bf55,
0xbf5fbe163f7abf0e,0x3ecfbf803ea13f46,0x3f423eacbf803ec4,0xbf133f78bdfbbf62,0xbf1dbf043f7cbe48,0x3f39bf67bd973f75,0x3ee63f2cbf6f0000,0xbf583f4e3e89bf7f,
0x3efcbf7d3e603f55,0x3f6a3d49bf733f22,0xbf273f71bcc9bf6d,0xbf51be793f7ebef1,0x3f4abf5cbe2f3f7b,0x3f313edbbf7f3e95,0xbf653f3e3eb8bf80,0xbf09bf183f77bdc9,
0x3f6dbf35bec43f80,0x3ec43f35bf6d0000,0xbf6d3f353ec4bf80,0xbec4bf353f6d0000,0x3f6dbf35bec43f80,0x3ec43f35bf6d0000,0xbf6d3f353ec4bf80,0xbec4bf353f6d0000,
0x3ec43f35bf6d8000,0xbf6d3f353ec4bf80,0xbec4bf353f6d8000,0x3f6dbf35bec43f80,0x3ec43f35bf6d8000,0xbf6d3f353ec4bf80,0xbec4bf353f6d8000,0x3f6dbf35bec43f80,
0x3dfb3f5cbf51be48,0xbf803edb3f27bf75,0xbea1bf3e3f6a0000,0x3f7abf18befc3f7f,0xbe893f7dbf09bf0e,0xbf6f3d493f65bf46,0x3d97bf713f313ec4,0x3f7cbe79bf4a3f62,
0xbf7e3f043f13bf7b,0xbcc9bf673f423e95,0x3f73bf2cbecf3f80,0x3e603f4ebf5fbdc9,0xbf773e163f58bf55,0x3eb8bf803ee63f22,0x3f7fbeacbf393f6d,0xbe2f3f78bf1dbef1,
0xbf5cbdc93f71bf35,0x3f2cbf753e163f55,0x3f183ef1bf803ec4,0xbf673f463e79bf7b,0xbf783f223edbbf80,0xbd49bf623f4e3e48,0x3f7dbe95bf3e3f6d,0xbeac3f7fbf04bf0e,
0x3f04bf7f3eac3f35,0x3f3e3e95bf7d3f0e,0xbf4e3f623d49bf6d,0xbedbbf223f78be48,0xbe79bf463f678000,0x3f80bef1bf183f7b,0xbe163f75bf2cbec4,0xbf713dc93f5cbf55,
0x3f80bedbbf1d3f7b,0xbea13f7dbf13bef1,0xbf583f5c3d97bf6d,0xbe89bf3e3f6fbdc9,0x3ecfbf803efc3f0e,0x3f423e79bf7a3f22,0x3e2f3f4ebf650000,0xbf7e3eac3f31bf75,
0xbcc93f67bf4abe48,0xbf733e163f51bf62,0xbf09bf043f7fbec4,0x3f77bf2cbeb83f7f,0x3f6abd49bf5f3f55,0xbf273f78be60bf46,0xbf7c3f183ee6bf80,0x3dfbbf713f393e95,
0x3f7fbf0ebef13f80,0xbe953f7bbf22bec4,0xbf46be483f75bf35,0x3f62bf55bdc93f6d,0x3dc93f55bf620000,0xbf753e483f46bf6d,0x3f22bf7b3e953f35,0x3ef13f0ebf7f3ec4,
0x3dc93f55bf628000,0xbf753e483f46bf6d,0x3f22bf7b3e953f35,0x3ef13f0ebf7f3ec4,0xbf7f3f0e3ef1bf80,0x3e95bf7b3f223ec4,0x3f463e48bf753f35,0xbf623f553dc9bf6d,
0xbf513f67bd97bf55,0xbdfbbf4e3f6abdc9,0xbcc9bf5c3f5f0000,0x3f65bd49bf583f62,0xbe60bf3e3f73be48,0x3f77be79bf393f75,0x3f6fbe16bf4a3f6d,0xbf423f71be2fbf46,
0xbf13bedb3f7fbf0e,0x3f7ebf18becf3f7f,0x3f80bf04befc3f80,0xbee63f80bf09bef1,0x3f7abf2cbea13f7b,0xbe893f78bf31be95,0xbeb83f7dbf1dbec4,0xbf27beac3f7cbf22,
0x3f3ebf753e793f35,0x3e163f46bf713e48,0xbf673dc93f4ebf6d,0x3f5cbf623d493f55,0xbf803ef13f04bf80,0x3f18bf7f3edb3f0e,0x3eac3f22bf7d3ec4,0xbf783e953f2cbf7b,
0x3f2c3e95bf783f35,0xbf7d3f223eacbf7b,0x3edbbf7f3f183ec4,0x3f043ef1bf803f0e,0x3d49bf623f5c8000,0x3f4e3dc9bf673f55,0xbf713f463e16bf6d,0x3e79bf753f3e3e48,
0xbf653f5cbcc9bf55,0x3e60bf713f4a3dc9,0xbe89bf2c3f7cbec4,0x3f6abe16bf423f75,0x3f7fbf18beb83f7b,0xbf133f80befcbef1,0xbdfb3f67bf580000,0xbf31be793f73bf46,
0xbee6bf043f80bf0e,0x3f7abeacbf1d3f7f,0x3f77bf3ebe2f3f6d,0xbecf3f7dbf27be95,0x3d973f4ebf6f3e48,0xbf51bd493f5fbf62,0xbf7e3edb3f09bf80,0x3f39bf783ea13f22,
0x3f7bbec4bf0e3f80,0xbf553f6dbe48bf35,0x3e48bf6d3f550000,0x3f0e3ec4bf7b3f35,0xbf7b3ec43f0ebf80,0x3f55bf6d3e483f35,0xbe483f6dbf550000,0xbf0ebec43f7bbf35,
0xbe483f6dbf558000,0xbf0ebec43f7bbf35,0x3f7bbec4bf0e3f80,0xbf553f6dbe48bf35,0x3e48bf6d3f558000,0x3f0e3ec4bf7b3f35,0xbf7b3ec43f0ebf80,0x3f55bf6d3e483f35,
0xbf653e163f39bf7b,0x3f7abf3ebdfb3f62,0x3e89bf713f510000,0x3ecf3f04bf7f3f22,0x3f273e79bf6f3f55,0xbf7c3edb3efcbf7f,0xbf1d3f80bf09bec4,0xbcc9bf4e3f73be95,
0x3ee6bf7d3f313e48,0x3e603f2cbf7e3ef1,0x3f77beacbf133f80,0xbf6a3f5cbd97bf46,0xbf423f78beb8bf0e,0x3e2fbf673f5fbdc9,0xbf4abd493f58bf6d,0x3f80bf18bea13f75,
0x3edb3ef1bf7d3f35,0xbf5c3dc93f3ebf7b,0x3f80bf22be793f6d,0xbf4e3f75beacbf0e,0xbf713e953f18bf80,0x3f78bf46bd493f55,0xbf2c3f7fbf04bec4,0x3e16bf623f67be48,
0xbf673f62be16bf35,0x3f04bf7f3f2c3e48,0x3d493f46bf783ec4,0xbf18be953f71bf55,0x3eacbf753f4e8000,0x3e793f22bf803f0e,0xbf3ebdc93f5cbf6d,0x3f7dbef1bedb3f7b,
0x3f13bf803f273e48,0xbdfb3f5cbf6f3e95,0x3f80bf18be893f6d,0xbf653f67be60bf22,0x3f093eacbf733f55,0xbf5f3e163f31bf7f,0xbecf3f78bf4a0000,0xbd97bf3e3f7cbef1,
0x3f51bd49bf423f7b,0xbf7e3f043eb8bf75,0xbcc93f4ebf773ec4,0xbee6bedb3f7abf46,0xbf583f71bea1bf0e,0x3efcbf7d3f393dc9,0xbf6a3e793f1dbf80,0x3f7fbf2cbe2f3f62,
0x3f62be48bf223f80,0xbf7f3f0e3e95bf6d,0x3f75bf553dc93f35,0xbf463f7bbef1bec4,0x3ef1bf7b3f460000,0xbdc93f55bf753ec4,0xbe95bf0e3f7fbf35,0x3f223e48bf623f6d,
0xbef13f7bbf468000,0x3dc9bf553f75bec4,0x3e953f0ebf7f3f35,0xbf22be483f62bf6d,0x3f62be48bf223f80,0xbf7f3f0e3e95bf6d,0x3f75bf553dc93f35,0xbf463f7bbef1bec4,
0xbcc9bf3e3f7ebf0e,0x3ea13f04bf7c3f46,0x3f09bf7d3f420000,0xbe893f67bf6a3e95,0xbf6f3eac3efcbf7b,0x3f7fbf18be603f62,0xbf13be793f65bf6d,0x3f4abd49bf393f7f,
0x3f80bf2cbdfb3f55,0xbf733f5cbe2fbf22,0x3f58be16bf273f80,0xbf773edb3ecfbf75,0x3eb8bf713f5fbe48,0xbd973f4ebf7a3ef1,0x3f51bf783ee63ec4,0xbf1d3f80bf31bdc9,
0xbf7d3f46bd49bf35,0x3f71bf623e793f0e,0xbf5c3f75bedbbec4,0x3f3ebf7f3f183e48,0xbf4e3dc93f2cbf80,0x3f67be95bf043f7b,0xbf783ef13eacbf6d,0x3f80bf22be163f55,
0xbe16bf223f80bf35,0x3eac3ef1bf783f55,0xbf04be953f67bf6d,0x3f2c3dc9bf4e3f7b,0x3f18bf7f3f3e8000,0xbedb3f75bf5c3e48,0x3e79bf623f71bec4,0xbd493f46bf7d3f0e,
0xbdfb3f4ebf7c3f0e,0x3cc9bf3e3f7fbf22,0xbea13f67bf6f3ec4,0x3e60bf5c3f77bef1,0xbefc3f78bf583e48,0x3ecfbf713f65be95,0xbf273f80bf390000,0x3f13bf7d3f4abdc9,
0xbf7e3f183e2fbf55,0x3f80bf2cbd973f46,0xbf733edb3eb8bf6d,0x3f7abf04be893f62,0xbf5f3e793f09bf7b,0x3f6abeacbee63f75,0xbf423d493f31bf80,0x3f51be16bf1d3f7f,
0xbf8000003f80,0xbf8000003f80,0xbf8000003f80,0xbf8000003f80,0xbf8000003f80,0xbf8000003f80,0xbf8000003f80,0xbf8000003f80,
0x3f808000bf808000,0x3f808000bf808000,0x3f808000bf808000,0x3f808000bf808000,0x3f808000bf808000,0x3f808000bf808000,0x3f808000bf808000,0x3f808000bf808000,
0xbefcbf5c3f093f55,0xbecfbf673ee63f62,0xbf27bf3e3f313f35,0xbf13bf4e3f1d3f46,0xbdfbbf7d3e2f3f7b,0xbcc9bf803d973f7f,0xbea1bf713eb83f6d,0xbe60bf783e893f75,
0x3f5fbf04bf583f0e,0x3f6abedbbf653ef1,0x3f42bf2cbf393f35,0x3f51bf18bf4a3f22,0x3f7ebe16bf7c3e48,0x3f80bd49bf7f3dc9,0x3f73beacbf6f3ec4,0x3f7abe79bf773e95,
0xbf18bf463f2c3f35,0xbedbbf623f043f55,0xbe79bf753eac3f6d,0xbd49bf7f3e163f7b,0xbf7dbdc93f800000,0xbf71be953f783e48,0xbf5cbef13f673ec4,0xbf3ebf223f4e3f0e,
0x3f4ebf22bf3e3f35,0x3f67bef1bf5c3f0e,0x3f78be95bf713ec4,0x3f80bdc9bf7d3e48,0x3e16bf7fbd493f80,0x3eacbf75be793f7b,0x3f04bf62bedb3f6d,0x3f2cbf46bf183f55,
0xbeb8bf673efc3f55,0xbd97bf7d3e603f75,0xbf51bf043f653ec4,0xbf1dbf3e3f393f22,0xbf803d493f7ebe48,0xbf73be793f7c3dc9,0xbf583f183f42bf35,0xbf773eac3f6abef1,
0x3f6fbedbbf5f3f0e,0x3f7fbe16bf7a3e95,0x3f13bf5cbee63f6d,0x3f4abf2cbf313f46,0x3cc9bf803dfb3f7b,0x3ea1bf78be2f3f7f,0xbf09bf4e3f273f35,0xbe89bf713ecf3f62,
0xbe953f7b3dc9bf80,0xbf223f553ef1bf6d,0xbf623f0e3f46bf35,0xbf7f3e483f75bec4,0xbf75be483f7f0000,0xbf46bf0e3f623ec4,0xbef1bf553f223f35,0xbdc9bf7b3e953f6d,
0xbf75be483f7f8000,0xbf46bf0e3f623ec4,0xbef1bf553f223f35,0xbdc9bf7b3e953f6d,0x3e95bf7bbdc93f80,0x3f22bf55bef13f6d,0x3f62bf0ebf463f35,0x3f7fbe48bf753ec4,
0xbf093f673ea1bf7b,0xbf5f3f183f39bf46,0x3ecf3f5cbf1dbf35,0xbd973f80be2fbf75,0xbf13bf3e3f423f0e,0xbdfbbf783eb83f62,0xbf803e163f77bec4,0xbf65beac3f7a3dc9,
0xbf58bedb3f733e48,0xbefcbf4e3f313f22,0xbf6a3f043f4abf35,0xbf7f3d493f7cbe95,0x3f51bf2cbf273f55,0x3f7ebe79bf6f3ef1,0xbcc9bf7d3e893f6d,0x3ee6bf71be603f7f,
0xbf713ef13f4ebf35,0xbf78bdc93f80be48,0xbf2cbf223f5c3ec4,0xbe16bf753edb3f55,0x3f673e95bf7d0000,0x3f043f46bf3ebf0e,0xbd493f7fbe79bf6d,0xbf183f623eacbf7b,
0xbeacbf623f183f35,0x3e79bf7f3d493f7b,0x3f3ebf46bf043f6d,0x3f7dbe95bf673f0e,0xbedb3f753e16bf80,0xbf5c3f223f2cbf55,0xbf803dc93f78bec4,0xbf4ebef13f713e48,
0xbf42bf043f6f3e48,0xbe2fbf713efc3f46,0xbf4a3f3e3f09bf6d,0xbf803e163f73bef1,0x3ee63f4ebf39bf0e,0xbe603f80bdfbbf75,0x3f77bedbbf513f35,0x3f6a3e79bf7f3dc9,
0x3f27bf5cbeb83f7b,0x3f7cbeacbf5f3f22,0xbf1dbf2c3f583ec4,0x3cc9bf7d3ea13f62,0xbf653f183f31bf55,0xbf7abd493f7ebe95,0x3e893f67bf13bf35,0xbecf3f783d97bf7f,
0x3f0ebf6dbe483f80,0x3f7bbec4bf553f35,0x3f553ec4bf7b0000,0x3e483f6dbf0ebf35,0xbf0e3f6d3e48bf80,0xbf7b3ec43f55bf35,0xbf55bec43f7b0000,0xbe48bf6d3f0e3f35,
0x3f553ec4bf7b8000,0x3e483f6dbf0ebf35,0xbf0e3f6d3e48bf80,0xbf7b3ec43f55bf35,0xbf55bec43f7b8000,0xbe48bf6d3f0e3f35,0x3f0ebf6dbe483f80,0x3f7bbec4bf553f35,
0x3f7fbe16bf6f3f0e,0x3f133f2cbf5fbe95,0xbdfbbf713f093f35,0x3f31bf5cbea13f7f,0xbf65be793f80be48,0xbe60bf673f1d3f22,0xbe893f80be2fbf6d,0xbf6a3f183f27bf62,
0xbd973f7dbeb8bf55,0xbf513f3e3efcbf75,0x3f7ebeacbf583f35,0x3f393f04bf73bdc9,0x3ee6bf78bcc93f7b,0x3f7abedbbf4a3f46,0xbf77bd493f7cbec4,0xbecfbf4e3f423ef1,
0x3d493f75bf04bf35,0xbf4e3f463edbbf7b,0xbf71bdc93f7dbec4,0xbe79bf623f2c3f0e,0xbf3ebef13f780000,0x3e16bf7f3eac3f55,0x3f67bf22bf183f6d,0x3f5c3e95bf803e48,
0xbf803e953f5cbf35,0xbf18bf223f673e48,0x3eacbf7f3e163f6d,0x3f78bef1bf3e3f55,0x3f2cbf62be793f80,0x3f7dbdc9bf713f0e,0x3edb3f46bf4ebec4,0xbf043f753d49bf7b,
0xbf7a3d493f73bf0e,0xbe89bf5c3f393ef1,0x3eb83f4ebf4abec4,0xbf273f673e2fbf7f,0x3f13bf71bd973f7b,0x3f7ebe16bf6a3f22,0xbf803e793f5fbf35,0xbee6bf3e3f583e95,
0x3e60bf803ea13f55,0x3f77bf04bf313f62,0xbf6f3f183f1dbf6d,0xbf42bedb3f7cbdc9,0x3f513eacbf7f3e48,0xbdfb3f7dbecfbf46,0x3cc9bf783efc3f35,0x3f65bf2cbf093f75,
0xbf463f553e95bf80,0xbf62be483f7fbec4,0x3dc9bf7b3ef13f35,0x3f75bf0ebf223f6d,0x3f223f0ebf750000,0xbef13f7bbdc9bf6d,0xbf7f3e483f62bf35,0xbe95bf553f463ec4,
0xbf22bf0e3f758000,0x3ef1bf7b3dc93f6d,0x3f7fbe48bf623f35,0x3e953f55bf46bec4,0xbf463f553e95bf80,0xbf62be483f7fbec4,0x3dc9bf7b3ef13f35,0x3f75bf0ebf223f6d,
0xbecfbf3e3f5f3e48,0x3f42bf5cbe603f7f,0xbe2f3f7dbee6bf35,0xbf7e3edb3f39bf62,0xbf803eac3f4abf55,0xbea1bf4e3f513e95,0x3f583e79bf7f3ec4,0xbe893f80beb8bf46,
0x3f6abf2cbefc3f7b,0x3f273f04bf7a3dc9,0xbf7c3e163f65bf35,0xbdfbbf673f313ef1,0xbcc9bf713f1d3f0e,0x3f73bf18bf133f75,0xbf093f78bd97bf6d,0xbf773d493f6fbf22,
0x3f78bdc9bf673f35,0xbd493f75bf18bf0e,0xbf7d3ef13f2cbf6d,0xbeacbf463f5c3e48,0x3f043f22bf710000,0xbf3e3f623e16bf7b,0xbf4ebe953f80bec4,0x3edbbf7f3e793f55,
0xbe793f7fbedbbf35,0xbf803e953f4ebf55,0xbe16bf623f3e3ec4,0x3f71bf22bf043f7b,0xbf5c3f463eacbf80,0xbf2cbef13f7dbe48,0x3f18bf753d493f6d,0x3f673dc9bf783f0e,
0xbf773f183f09bf7b,0xbeb8bf3e3f653dc9,0x3f7fbedbbf313f6d,0x3e2f3f5cbf4abe95,0xbf7e3e793f51bf55,0x3cc9bf713f273ef1,0x3f73bd49bf6a3f35,0xbe603f7dbefcbf22,
0xbe89bf4e3f583e48,0x3f6fbf2cbee63f7f,0x3d973f67bf39bec4,0xbf7c3f043f1dbf75,0x3dfbbf783f133f0e,0x3f80beacbf423f62,0xbea13f80becfbf35,0xbf7a3e163f5fbf46,
0x3f6dbf35bec43f80,0x3ec43f35bf6d0000,0xbf6d3f353ec4bf80,0xbec4bf353f6d0000,0x3f6dbf35bec43f80,0x3ec43f35bf6d0000,0xbf6d3f353ec4bf80,0xbec4bf353f6d0000,
0x3ec43f35bf6d8000,0xbf6d3f353ec4bf80,0xbec4bf353f6d8000,0x3f6dbf35bec43f80,0x3ec43f35bf6d8000,0xbf6d3f353ec4bf80,0xbec4bf353f6d8000,0x3f6dbf35bec43f80,
0xbf1d3f78be2fbf55,0xbf39beac3f7fbef1,0x3ee6bf803eb83f35,0x3f583e16bf773f22,0xbf5f3f4e3e60bf7b,0xbecfbf2c3f73bdc9,0x3f42bf67bcc93f6d,0x3f133f04bf7e3e95,
0xbf4abe793f7cbf0e,0x3f31bf713d973f62,0x3f653d49bf6f3f35,0xbf093f7dbe89bf46,0xbefcbf183f7abe48,0x3f6abf3ebea13f7f,0x3f273edbbf803ec4,0xbf513f5c3dfbbf75,
0x3f04bf7f3eac3f35,0x3f3e3e95bf7d3f0e,0xbf4e3f623d49bf6d,0xbedbbf223f78be48,0xbe79bf463f670000,0x3f80bef1bf183f7b,0xbe163f75bf2cbec4,0xbf713dc93f5cbf55,
0x3f5c3dc9bf713f35,0xbf2c3f75be16bf55,0xbf18bef13f80bec4,0x3f67bf46be793f7b,0x3f78bf22bedb3f80,0x3d493f62bf4ebe48,0xbf7d3e953f3ebf6d,0x3eacbf7f3f043f0e,
0xbf393f71bdfbbf55,0xbee6bf183f7cbe95,0x3e60bf783f273ec4,0x3f5f3d49bf6a3f46,0x3eb83f2cbf773e48,0xbf7f3f043f09bf7f,0xbf51be163f73bf35,0x3f4abf673cc93f62,
0xbf31beac3f7ebf0e,0x3f65bf4ebe2f3f75,0x3f7abe79bf423f6d,0xbefc3f80becfbf22,0xbf6f3f3e3e89bf7b,0xbd97bf5c3f583dc9,0x3f13bf7d3ea13f35,0x3f1d3edbbf803ef1,
0xbf7f3f0e3ef1bf80,0x3e95bf7b3f223ec4,0x3f463e48bf753f35,0xbf623f553dc9bf6d,0xbdc9bf553f620000,0x3f75be48bf463f6d,0xbf223f7bbe95bf35,0xbef1bf0e3f7fbec4,
0xbdc9bf553f628000,0x3f75be48bf463f6d,0xbf223f7bbe95bf35,0xbef1bf0e3f7fbec4,0x3f7fbf0ebef13f80,0xbe953f7bbf22bec4,0xbf46be483f75bf35,0x3f62bf55bdc93f6d,
0x3f7cbeacbf273f7b,0xbf1d3f7dbeb8bf22,0xbf313f78be89bf35,0xbea1bf2c3f7abe95,0xbf093f80bee6bf0e,0xbefcbf043f80bef1,0xbecfbf183f7ebec4,0x3f7fbedbbf133f7f,
0xbe2f3f71bf42be48,0xbf4abe163f6fbf46,0xbf39be793f77bf35,0x3f73bf3ebe603f75,0xbf58bd493f65bf55,0x3f5fbf5cbcc93f62,0x3f6abf4ebdfb3f6d,0xbd973f67bf51bdc9,
0xbf2cbe953f78bf35,0x3f7dbf22beac3f7b,0xbedb3f7fbf18bec4,0xbf04bef13f80bf0e,0xbd493f62bf5c0000,0xbf4ebdc93f67bf55,0x3f71bf46be163f6d,0xbe793f75bf3ebe48,
0x3f3ebf753e793f35,0x3e163f46bf713e48,0xbf673dc93f4ebf6d,0x3f5cbf623d493f55,0xbf803ef13f04bf80,0x3f18bf7f3edb3f0e,0x3eac3f22bf7d3ec4,0xbf783e953f2cbf7b,
0xbea13f78bf39be48,0xbf09bedb3f7ebf22,0xbf5f3d493f51bf6d,0x3f6fbf4ebd973f62,0x3f27bf7d3ecf3f0e,0x3e2f3f3ebf773e95,0x3f1d3eacbf7a3f35,0xbf803f043ee6bf7f,
0xbf733e793f31bf7b,0x3f58bf673dfb3f46,0x3efcbf803f133ec4,0x3eb83f18bf7f3ef1,0x3f423e16bf6a3f55,0xbf7c3f2c3e89bf75,0xbf4a3f71be60bf35,0x3cc9bf5c3f65bdc9,
0x3f7bbec4bf0e3f80,0xbf553f6dbe48bf35,0x3e48bf6d3f550000,0x3f0e3ec4bf7b3f35,0xbf7b3ec43f0ebf80,0x3f55bf6d3e483f35,0xbe483f6dbf550000,0xbf0ebec43f7bbf35,
0xbe483f6dbf558000,0xbf0ebec43f7bbf35,0x3f7bbec4bf0e3f80,0xbf553f6dbe48bf35,0x3e48bf6d3f558000,0x3f0e3ec4bf7b3f35,0xbf7b3ec43f0ebf80,0x3f55bf6d3e483f35,
0xbea1bf183f80bf0e,0x3f58bd49bf4a3f75,0x3f5fbf673e2f3f35,0xbeb83f78bf42bdc9,0xbd973f5cbf6a3e48,0xbf13beac3f77bf46,0xbf7e3f2c3e60bf6d,0x3f31bf7d3ee63ef1,
0x3f73bf4ebcc93f55,0xbf093f80bf1dbe95,0x3efc3edbbf7c3f35,0xbf6f3e793f27bf7f,0xbf7f3f043ecfbf7b,0x3f51bf713e893f22,0xbdfbbf3e3f7abec4,0x3f393e16bf653f62,
0xbf673f62be16bf35,0x3f04bf7f3f2c3e48,0x3d493f46bf783ec4,0xbf18be953f71bf55,0x3eacbf753f4e0000,0x3e793f22bf803f0e,0xbf3ebdc93f5cbf6d,0x3f7dbef1bedb3f7b,
0xbedbbef13f7dbf35,0x3f5cbdc9bf3e3f7b,0xbf803f223e79bf6d,0x3f4ebf753eac3f0e,0x3f71be95bf183f80,0xbf783f463d49bf55,0x3f2cbf7f3f043ec4,0xbe163f62bf673e48,
0x3e2f3f2cbf7f3f0e,0xbf1dbe793f6abf62,0xbf393f7dbefcbec4,0x3ea1bf713f58bdc9,0xbf7a3edb3ee6bf7b,0x3f77bf4e3cc93f46,0xbeb8bf043f7ebf35,0x3f423d49bf513f75,
0xbf7c3f3e3d97bf55,0x3f4abf783ecf3ef1,0xbf31be163f5fbf6d,0x3f73beacbf093f7f,0x3e60bf673f65be48,0x3e893f18bf803f22,0x3f6fbf5c3dfb3f35,0xbf273f80bf13be95,
0xbf623e483f22bf80,0x3f7fbf0ebe953f6d,0xbf753f55bdc9bf35,0x3f46bf7b3ef13ec4,0xbef13f7bbf460000,0x3dc9bf553f75bec4,0x3e953f0ebf7f3f35,0xbf22be483f62bf6d,
0x3ef1bf7b3f468000,0xbdc93f55bf753ec4,0xbe95bf0e3f7fbf35,0x3f223e48bf623f6d,0xbf623e483f22bf80,0x3f7fbf0ebe953f6d,0xbf753f55bdc9bf35,0x3f46bf7b3ef13ec4,
0xbf313f80bf1dbe48,0x3ee6bf783f51bdc9,0xbf7a3f4ebd97bf35,0x3f5fbf713eb83ef1,0x3ecf3edbbf773f55,0xbf27be163f58bf75,0xbe2f3f5cbf733ec4,0xbdfbbf2c3f80bf22,
0xbf39bd493f4abf7b,0x3f65be79bf133f7f,0xbe60bf183f7fbf35,0x3efc3eacbf6f3f62,0xbf6a3f67be89bf0e,0x3f42bf7d3f093e95,0xbf7c3f043ea1bf6d,0x3f7ebf3ebcc93f46,
0x3e163f22bf803f35,0xbeacbef13f78bf55,0x3f043e95bf673f6d,0xbf2cbdc93f4ebf7b,0xbf183f7fbf3e0000,0x3edbbf753f5cbe48,0xbe793f62bf713ec4,0x3d49bf463f7dbf0e,
0xbf7d3f46bd49bf35,0x3f71bf623e793f0e,0xbf5c3f75bedbbec4,0x3f3ebf7f3f183e48,0xbf4e3dc93f2cbf80,0x3f67be95bf043f7b,0xbf783ef13eacbf6d,0x3f80bf22be163f55,
0x3f1d3e16bf513f7b,0xbf31bd493f42bf7f,0x3ee63eacbf6a3f6d,0xbf09be793f5fbf75,0x3e893f04bf7a3f55,0xbeb8bedb3f73bf62,0x3d973f2cbf803f35,0xbe2fbf183f7ebf46,
0xbf4a3f7dbf13be48,0x3f39bf803f273dc9,0xbf653f71becfbec4,0x3f58bf783efc3e95,0xbf773f5cbe60bf0e,0x3f6fbf673ea13ef1,0xbf7f3f3ebcc9bf35,0x3f7cbf4e3dfb3f22,
0xbf3500003f353f80,0x3f350000bf35bf80,0xbf3500003f353f80,0x3f350000bf35bf80,0xbf3500003f353f80,0x3f350000bf35bf80,0xbf3500003f353f80,0x3f350000bf35bf80,
0xbf35bf80bf358000,0x3f353f803f358000,0xbf35bf80bf358000,0x3f353f803f358000,0xbf35bf80bf358000,0x3f353f803f358000,0xbf35bf80bf358000,0x3f353f803f358000,
0xbe893e79be603e48,0xbeb83eacbea13e95,0xbd973d49bcc90000,0xbe2f3e16bdfb3dc9,0xbf1d3f18bf133f0e,0xbf313f2cbf273f22,0xbee63edbbecf3ec4,0xbf093f04befc3ef1,
0xbf773f78bf7a3f7b,0xbf6f3f71bf733f75,0xbf7f3f80bf803f80,0xbf7c3f7dbf7e3f7f,0xbf4a3f4ebf513f55,0xbf393f3ebf423f46,0xbf653f67bf6a3f6d,0xbf583f5cbf5f3f62,
0x3f18bf223f2cbf35,0x3edbbef13f04bf0e,0x3e79be953eacbec4,0x3d49bdc93e16be48,0x3f7dbf7f3f80bf80,0x3f71bf753f78bf7b,0x3f5cbf623f67bf6d,0x3f3ebf463f4ebf55,
0xbf4e3f46bf3e3f35,0xbf673f62bf5c3f55,0xbf783f75bf713f6d,0xbf803f7fbf7d3f7b,0xbe163dc9bd498000,0xbeac3e95be793e48,0xbf043ef1bedb3ec4,0xbf2c3f22bf183f0e,
0x3f6abf713f77bf7b,0x3f42bf4e3f58bf62,0x3f7cbf783f73bf6d,0x3f7ebf803f80bf7f,0x3f39bf2c3f1dbf0e,0x3f65bf5c3f51bf46,0x3e60be163d970000,0x3efcbedb3eb8be95,
0xbecf3eacbe893e48,0xbf273f18bf093ef1,0x3e2fbe793ea1bec4,0xbdfb3d493cc9bdc9,0x3f31bf3e3f4abf55,0x3ee6bf043f13bf22,0x3f7abf7d3f7fbf80,0x3f5fbf673f6fbf75,
0xbf753f7bbf7f3f80,0xbf463f55bf623f6d,0xbef13f0ebf223f35,0xbdc93e48be953ec4,0x3e95be483dc90000,0x3f22bf0e3ef1bec4,0x3f62bf553f46bf35,0x3f7fbf7b3f75bf6d,
0x3e95be483dc98000,0x3f22bf0e3ef1bec4,0x3f62bf553f46bf35,0x3f7fbf7b3f75bf6d,0x3f75bf7b3f7fbf80,0x3f46bf553f62bf6d,0x3ef1bf0e3f22bf35,0x3dc9be483e95bec4,
0xbf7a3f71bf653f55,0xbf773f7dbf803f7f,0xbeb83e79bdfb0000,0xbf423f2cbf133ef1,0x3e2fbd49bd973e48,0x3f1dbf043ecfbe95,0xbf393f4ebf5f3f6d,0xbea13edbbf093f22,
0xbe603eacbee63f0e,0x3e89be163cc93dc9,0xbf6f3f78bf7e3f80,0xbf273f3ebf513f62,0x3f7cbf803f7fbf7b,0x3f4abf5c3f6abf75,0x3f31bf183efcbec4,0x3f73bf673f58bf46,
0xbf713f62bf4e3f35,0xbf783f7fbf803f7b,0xbf2c3f46bf5c3f6d,0xbe163e95bedb3f0e,0x3f67bf753f7dbf80,0x3f04bf223f3ebf55,0xbd49bdc93e79bec4,0xbf183ef1beac3e48,
0xbeac3ef1bf183f35,0x3e79bdc9bd493e48,0x3f3ebf223f04bec4,0x3f7dbf753f67bf55,0xbedb3e95be168000,0xbf5c3f46bf2c3f0e,0xbf803f7fbf783f6d,0xbf4e3f62bf713f7b,
0xbf7f3f78bf6a3f55,0xbf513f67bf773f7f,0xbdfbbd493e60bec4,0xbf393f18bee63e95,0x3f73bf7d3f80bf7b,0x3f09bf2c3f4abf62,0x3efcbeac3e2f0000,0x3f6fbf5c3f42bf22,
0xbd973e79becf3f0e,0x3f13bedb3e89bdc9,0xbf7e3f80bf7a3f6d,0xbf313f4ebf653f75,0xbea13e163cc9be48,0xbf583f3ebf1d3ef1,0x3f5fbf713f7cbf80,0x3eb8bf043f27bf46,
0xbf553f6dbf7b3f80,0xbe483ec4bf0e3f35,0x3f0ebec43e480000,0x3f7bbf6d3f55bf35,0x3f55bf6d3f7bbf80,0x3e48bec43f0ebf35,0xbf0e3ec4be480000,0xbf7b3f6dbf553f35,
0x3f0ebec43e488000,0x3f7bbf6d3f55bf35,0x3f55bf6d3f7bbf80,0x3e48bec43f0ebf35,0xbf0e3ec4be488000,0xbf7b3f6dbf553f35,0xbf553f6dbf7b3f80,0xbe483ec4bf0e3f35,
0xbf273f4ebf6a3f7b,0x3e2f3d49be893ef1,0xbf1d3edbbe600000,0xbf803f78bf653f46,0x3ea1bf043f31bf55,0xbf093eacbdfbbdc9,0x3f5fbf3e3f13bec4,0x3f6fbf7d3f7fbf75,
0x3f42bf183ecfbe48,0x3f7cbf803f77bf62,0xbf4a3f67bf7a3f80,0xbcc93e79bee63f22,0xbf733f5cbf393f0e,0xbf583f71bf7e3f7f,0x3efcbf2c3f51bf6d,0xbeb83e163d97be95,
0xbd493e95bf043f35,0x3f4ebf223edbbe48,0x3f71bf7f3f7dbf6d,0x3e79bef13f2cbf55,0x3f3ebf623f78bf80,0xbe16bdc93eacbf0e,0xbf673f46bf183ec4,0xbf5c3f75bf803f7b,
0x3f80bf753f5cbf35,0x3f18bf463f67bf7b,0xbeac3dc93e16bec4,0xbf783f62bf3e3f0e,0xbf2c3ef1be798000,0xbf7d3f7fbf713f55,0xbedb3f22bf4e3f6d,0x3f04be953d493e48,
0x3f58bf2c3ee6be48,0x3f5fbf783f80bf75,0xbf6a3f7dbf7e3f6d,0xbd973eacbf133f46,0x3e2fbedb3f27bf55,0xbf4a3f18beb83dc9,0x3f39bf043e890000,0x3f73bf803f7abf62,
0x3f09bf3e3f65bf7b,0xbefc3e793cc9be95,0x3ecfbe16bdfb3ec4,0x3f7fbf713f51bf22,0xbf7c3f67bf423f0e,0xbf1d3f4ebf6f3f7f,0x3f31bf5c3f77bf80,0xbea13d493e60bef1,
0xbf223f55bf753f80,0x3ef1be48bdc93ec4,0x3f7fbf7b3f62bf35,0x3e95bf0e3f46bf6d,0xbf463f0ebe950000,0xbf623f7bbf7f3f6d,0x3dc93e48bef13f35,0x3f75bf553f22bec4,
0x3f46bf0e3e958000,0x3f62bf7b3f7fbf6d,0xbdc9be483ef1bf35,0xbf753f55bf223ec4,0xbf223f55bf753f80,0x3ef1be48bdc93ec4,0x3f7fbf7b3f62bf35,0x3e95bf0e3f46bf6d,
0x3eb8bd49be893f0e,0x3f7fbf783f58bf22,0xbf513f18bea10000,0xbf4a3f71bf803f75,0xbf393f67bf7e3f7b,0x3ee6be16be2f3ef1,0x3e60bf043f42bf6d,0xbf5f3f2cbecf3dc9,
0x3f6fbf803f77bf55,0xbd97be793f09bf46,0xbf133f4ebf733f80,0x3f1dbeac3cc93e95,0x3f31bedb3dfb3e48,0x3f65bf7d3f7cbf62,0xbf7a3f5cbf273ec4,0xbefc3f3ebf6a3f7f,
0x3f78bf7f3f67bf35,0xbd49be953f18bf55,0xbf7d3f62bf2c3ec4,0xbeac3f22bf5c3f7b,0x3f04bf463f71bf80,0xbf3e3ef1be16be48,0xbf4e3f75bf803f6d,0x3edbbdc9be793f0e,
0xbe79bdc93edbbf35,0xbf803f75bf4e3f0e,0xbe163ef1bf3e3f6d,0x3f71bf463f04be48,0xbf5c3f22beac8000,0xbf2c3f62bf7d3f7b,0x3f18be95bd493ec4,0x3f67bf7f3f78bf55,
0xbefc3e163e60bf0e,0xbf6a3f80bf733f46,0x3f27beacbcc93ec4,0x3f51bf783f7ebf62,0xbf4a3f04be2fbe48,0xbf313f67bf7f3f75,0x3f65bf2c3eb80000,0x3f09bf4e3f77bf7f,
0xbf5f3f7dbf7a3f55,0x3ecfbd49bea13f22,0x3f42bf713f80bf6d,0xbf133e793dfbbef1,0xbf1d3f5cbf7c3f7b,0x3f39bedb3d973e95,0x3ee6bf3e3f6fbf80,0xbf583f18be89bdc9,
0xbec43f35bf6d3f80,0x3f6dbf353ec40000,0x3ec4bf353f6dbf80,0xbf6d3f35bec40000,0xbec43f35bf6d3f80,0x3f6dbf353ec40000,0x3ec4bf353f6dbf80,0xbf6d3f35bec40000,
0x3f6dbf353ec48000,0x3ec4bf353f6dbf80,0xbf6d3f35bec48000,0xbec43f35bf6d3f80,0x3f6dbf353ec48000,0x3ec4bf353f6dbf80,0xbf6d3f35bec48000,0xbec43f35bf6d3f80,
0x3f7ebf5c3f13be48,0x3cc9bedb3f42bf75,0xbf733f3ebecf0000,0xbe603f18bf5f3f7f,0x3f77bf7d3f58bf0e,0xbeb8bd493ee6bf46,0xbf7f3f71bf393ec4,0x3e2f3e79bf1d3f62,
0x3dfbbf043f51bf7b,0xbf803f67bf273e95,0xbea13f2cbf6a3f80,0x3f7abf4e3efcbdc9,0xbe89be163f09bf55,0xbf6f3f80bf653f22,0x3d973eacbf313f6d,0x3f7cbf783f4abef1,
0xbf043dc93eacbf35,0xbf3e3f75bf7d3f55,0x3f4ebef13d493ec4,0x3edbbf463f78bf7b,0x3e79bf223f67bf80,0xbf803f62bf183e48,0x3e163e95bf2c3f6d,0x3f71bf7f3f5cbf0e,
0xbf5c3f7fbf713f35,0x3f2cbe95be163f0e,0x3f18bf623f80bf6d,0xbf673f22be79be48,0xbf783f46bedb8000,0xbd493ef1bf4e3f7b,0x3f7dbf753f3ebec4,0xbeacbdc93f04bf55,
0x3cc93edbbf4a3f7b,0x3f73bf7d3f51bef1,0x3f09bf5c3f7fbf6d,0xbf773f3ebeb8bdc9,0xbf6a3f80bf5f3f0e,0x3f27be79be603f22,0x3f7cbf4e3ee60000,0xbdfbbeac3f39bf75,
0x3f80bf673f1dbe48,0xbea1be163f13bf62,0xbf583f04bd97bec4,0xbe893f2cbf6f3f7f,0x3ecf3d49befc3f55,0x3f42bf783f7abf46,0x3e2fbf183f65bf80,0xbf7e3f71bf313e95,
0xbdc93f0ebf623f80,0x3f75bf7b3f46bec4,0xbf223e483e95bf35,0xbef13f55bf7f3f6d,0x3f7fbf553ef10000,0xbe95be483f22bf6d,0xbf463f7bbf753f35,0x3f62bf0e3dc93ec4,
0x3f7fbf553ef18000,0xbe95be483f22bf6d,0xbf463f7bbf753f35,0x3f62bf0e3dc93ec4,0x3dc9bf0e3f62bf80,0xbf753f7bbf463ec4,0x3f22be48be953f35,0x3ef1bf553f7fbf6d,
0x3f13bf673f7fbf55,0xbf7e3f4ebecfbdc9,0xbf803f5cbefc0000,0x3ee63d49bf093f62,0xbf7a3f3ebea1be48,0x3e893e79bf313f75,0x3eb83e16bf1d3f6d,0x3f27bf713f7cbf46,
0xbf513edb3d97bf0e,0xbdfb3f18bf6a3f7f,0xbcc93f04bf5f3f80,0x3f65bf803f58bef1,0xbe603f2cbf733f7b,0x3f77bf783f39be95,0x3f6fbf7d3f4abec4,0xbf423eac3e2fbf22,
0xbf2c3f75bf783f35,0x3f7dbf463eac3e48,0xbedbbdc93f18bf6d,0xbf043f62bf803f55,0xbd49bef13f5cbf80,0xbf4e3f7fbf673f0e,0x3f71bf223e163ec4,0xbe79be953f3ebf7b,
0x3f3ebe95be793f35,0x3e16bf223f71bf7b,0xbf673f7fbf4e3ec4,0x3f5cbef1bd493f0e,0xbf803f62bf048000,0x3f18bdc9bedb3f55,0x3eacbf463f7dbf6d,0xbf783f75bf2c3e48,
0x3ee6bf5c3f80bf55,0xbf7a3f71bf1d3dc9,0xbf773f2cbe2fbec4,0x3ecf3e16bf273f75,0xbd973f18bf6f3f7b,0x3f51bf803f5fbef1,0x3f7ebf673f090000,0xbf393e793ea1bf46,
0xbf653f043cc9bf0e,0x3e603eacbf4a3f7f,0xbe893f3ebf7c3f6d,0x3f6abf7d3f42be95,0x3f7fbf4e3eb83e48,0xbf133d493efcbf62,0xbdfbbedb3f58bf80,0xbf313f78bf733f22,
0x3e483ec4bf553f80,0x3f0ebf6d3f7bbf35,0xbf7b3f6dbf0e0000,0x3f55bec4be483f35,0xbe48bec43f55bf80,0xbf0e3f6dbf7b3f35,0x3f7bbf6d3f0e0000,0xbf553ec43e48bf35,
0x3f7bbf6d3f0e8000,0xbf553ec43e48bf35,0x3e483ec4bf553f80,0x3f0ebf6d3f7bbf35,0xbf7b3f6dbf0e8000,0x3f55bec4be483f35,0xbe48bec43f55bf80,0xbf0e3f6dbf7b3f35,
0xbee6be163f31bf7b,0xbe603f3ebf7e3f62,0xbf773f71bf130000,0x3f6abf04bd973f22,0x3f42be79beb83f55,0xbe2fbedb3f5fbf7f,0x3f4abf803f58bec4,0xbf803f4ebea1be95,
0xbf653f7dbf393e48,0x3f7abf2c3dfb3ef1,0x3e893eacbf513f80,0x3ecfbf5c3f7fbf46,0x3f27bf783f6fbf0e,0xbf7c3f67befcbdc9,0xbf1d3d493f09bf6d,0xbcc93f18bf733f75,
0x3f67bef1be163f35,0xbf04bdc93f2cbf7b,0xbd493f22bf783f6d,0x3f18bf753f71bf0e,0xbeacbe953f4ebf80,0xbe793f46bf803f55,0x3f3ebf7f3f5cbec4,0xbf7d3f62bedbbe48,
0x3edbbf623f7dbf35,0xbf5c3f7fbf3e3e48,0x3f80bf463e793ec4,0xbf4e3e953eacbf55,0xbf713f75bf188000,0x3f78bf223d493f0e,0xbf2c3dc93f04bf6d,0x3e163ef1bf673f7b,
0xbf513f80bf423e48,0x3f7ebf5c3eb83e95,0x3cc93f18bf773f6d,0x3ee6bf673f7abf22,0x3f58beacbea13f55,0xbefcbe163f39bf7f,0x3f6abf783f1d0000,0xbf7f3f3ebe2fbef1,
0x3f133d49bf273f7b,0xbdfbbf043f6fbf75,0x3f80bf4e3e893ec4,0xbf653edb3e60bf46,0x3f09bf713f73bf0e,0xbf5f3f7dbf313dc9,0xbecfbe793f4abf80,0xbd973f2cbf7c3f62,
0x3ef13e48bf463f80,0xbdc9bf0e3f75bf6d,0xbe953f55bf7f3f35,0x3f22bf7b3f62bec4,0xbf623f7bbf220000,0x3f7fbf553e953ec4,0xbf753f0e3dc9bf35,0x3f46be48bef13f6d,
0x3f62bf7b3f228000,0xbf7f3f55be95bec4,0x3f75bf0ebdc93f35,0xbf463e483ef1bf6d,0x3ef13e48bf463f80,0xbdc9bf0e3f75bf6d,0xbe953f55bf7f3f35,0x3f22bf7b3f62bec4,
0xbf803f3ebdfbbf0e,0x3f73bf04be2f3f46,0xbf583f7dbf270000,0x3f77bf673ecf3e95,0xbeb8beac3f5fbf7b,0x3d973f18bf7a3f62,0xbf513e793ee6bf6d,0x3f1d3d49bf313f7f,
0xbcc93f2cbf7e3f55,0x3ea1bf5c3f7cbf22,0x3f093e16bf423f80,0xbe89bedb3f6abf75,0xbf6f3f71befcbe48,0x3f7fbf4e3e603ef1,0xbf133f78bf653ec4,0x3f4abf803f39bdc9,
0x3e16bf463f80bf35,0xbeac3f62bf783f0e,0x3f04bf753f67bec4,0xbf2c3f7fbf4e3e48,0xbf18bdc93f3ebf80,0x3edb3e95bf5c3f7b,0xbe79bef13f71bf6d,0x3d493f22bf7d3f55,
0xbf7d3f223d49bf35,0x3f71bef1be793f55,0xbf5c3e953edbbf6d,0x3f3ebdc9bf183f7b,0xbf4e3f7fbf2c8000,0x3f67bf753f043e48,0xbf783f62beacbec4,0x3f80bf463e163f0e,
0x3f7ebf4e3e2f3f0e,0xbf803f3ebd97bf22,0x3f73bf673eb83ec4,0xbf7a3f5cbe89bef1,0x3f5fbf783f093e48,0xbf6a3f71bee6be95,0x3f42bf803f310000,0xbf513f7dbf1dbdc9,
0xbdfbbf183f7cbf55,0x3cc93f2cbf7f3f46,0xbea1bedb3f6fbf6d,0x3e603f04bf773f62,0xbefcbe793f58bf7b,0x3ecf3eacbf653f75,0xbf27bd493f39bf80,0x3f133e16bf4a3f7f,
0xbf3500003f353f80,0x3f350000bf35bf80,0xbf3500003f353f80,0x3f350000bf35bf80,0xbf3500003f353f80,0x3f350000bf35bf80,0xbf3500003f353f80,0x3f350000bf35bf80,
0xbf35bf80bf358000,0x3f353f803f358000,0xbf35bf80bf358000,0x3f353f803f358000,0xbf35bf80bf358000,0x3f353f803f358000,0xbf35bf80bf358000,0x3f353f803f358000,
0xbf5f3f5cbf583f55,0xbf6a3f67bf653f62,0xbf423f3ebf393f35,0xbf513f4ebf4a3f46,0xbf7e3f7dbf7c3f7b,0xbf803f80bf7f3f7f,0xbf733f71bf6f3f6d,0xbf7a3f78bf773f75,
0xbefc3f04bf093f0e,0xbecf3edbbee63ef1,0xbf273f2cbf313f35,0xbf133f18bf1d3f22,0xbdfb3e16be2f3e48,0xbcc93d49bd973dc9,0xbea13eacbeb83ec4,0xbe603e79be893e95,
0xbf4e3f46bf3e3f35,0xbf673f62bf5c3f55,0xbf783f75bf713f6d,0xbf803f7fbf7d3f7b,0xbe163dc9bd490000,0xbeac3e95be793e48,0xbf043ef1bedb3ec4,0xbf2c3f22bf183f0e,
0xbf183f22bf2c3f35,0xbedb3ef1bf043f0e,0xbe793e95beac3ec4,0xbd493dc9be163e48,0xbf7d3f7fbf803f80,0xbf713f75bf783f7b,0xbf5c3f62bf673f6d,0xbf3e3f46bf4e3f55,
0xbf6f3f67bf5f3f55,0xbf7f3f7dbf7a3f75,0xbf133f04bee63ec4,0xbf4a3f3ebf313f22,0xbcc9bd493dfbbe48,0xbea13e79be2f3dc9,0x3f09bf183f27bf35,0x3e89beac3ecfbef1,
0xbeb83edbbefc3f0e,0xbd973e16be603e95,0xbf513f5cbf653f6d,0xbf1d3f2cbf393f46,0xbf803f80bf7e3f7b,0xbf733f78bf7c3f7f,0xbf583f4ebf423f35,0xbf773f71bf6a3f62,
0x3f75bf7b3f7fbf80,0x3f46bf553f62bf6d,0x3ef1bf0e3f22bf35,0x3dc9be483e95bec4,0xbe953e48bdc90000,0xbf223f0ebef13ec4,0xbf623f55bf463f35,0xbf7f3f7bbf753f6d,
0xbe953e48bdc98000,0xbf223f0ebef13ec4,0xbf623f55bf463f35,0xbf7f3f7bbf753f6d,0xbf753f7bbf7f3f80,0xbf463f55bf623f6d,0xbef13f0ebf223f35,0xbdc93e48be953ec4,
0x3f58bf673f73bf7b,0x3efcbf183f31bf46,0x3f6abf5c3f4abf35,0x3f7fbf803f7cbf75,0xbf513f3ebf273f0e,0xbf7e3f78bf6f3f62,0x3cc9be163e89bec4,0xbee63eacbe603dc9,
0xbf093edbbea13e48,0xbf5f3f4ebf393f22,0x3ecfbf043f1dbf35,0xbd97bd493e2fbe95,0xbf133f2cbf423f55,0xbdfb3e79beb83ef1,0xbf803f7dbf773f6d,0xbf653f71bf7a3f7f,
0x3eacbef13f18bf35,0xbe793dc93d49be48,0xbf3e3f22bf043ec4,0xbf7d3f75bf673f55,0x3edbbe953e160000,0x3f5cbf463f2cbf0e,0x3f80bf7f3f78bf6d,0x3f4ebf623f71bf7b,
0xbf713f62bf4e3f35,0xbf783f7fbf803f7b,0xbf2c3f46bf5c3f6d,0xbe163e95bedb3f0e,0x3f67bf753f7dbf80,0x3f04bf223f3ebf55,0xbd49bdc93e79bec4,0xbf183ef1beac3e48,
0xbf273f04beb83e48,0xbf7c3f71bf5f3f46,0x3f1dbf3e3f58bf6d,0xbcc9be163ea1bef1,0x3f65bf4e3f31bf0e,0x3f7abf803f7ebf75,0xbe893edbbf133f35,0x3ecfbe793d973dc9,
0xbf423f5cbf6f3f7b,0xbe2f3eacbefc3f22,0xbf4a3f2cbf093ec4,0xbf803f7dbf733f62,0x3ee6bf183f39bf55,0xbe603d493dfbbe95,0x3f77bf673f51bf35,0x3f6abf783f7fbf7f,
0xbf553f6dbf7b3f80,0xbe483ec4bf0e3f35,0x3f0ebec43e480000,0x3f7bbf6d3f55bf35,0x3f55bf6d3f7bbf80,0x3e48bec43f0ebf35,0xbf0e3ec4be480000,0xbf7b3f6dbf553f35,
0x3f0ebec43e488000,0x3f7bbf6d3f55bf35,0x3f55bf6d3f7bbf80,0x3e48bec43f0ebf35,0xbf0e3ec4be488000,0xbf7b3f6dbf553f35,0xbf553f6dbf7b3f80,0xbe483ec4bf0e3f35,
0x3d973e16beb83f0e,0x3f51bf2c3efcbe95,0xbf7e3f71bf583f35,0xbf393f5cbf733f7f,0xbee63e79bcc9be48,0xbf7a3f67bf4a3f22,0x3f77bf803f7cbf6d,0x3ecfbf183f42bf62,
0x3f7fbf7d3f6fbf55,0x3f13bf3e3f5fbf75,0xbdfb3eacbf093f35,0x3f31bf043ea1bdc9,0xbf653f78bf803f7b,0xbe603edbbf1d3f46,0xbe893d493e2fbec4,0xbf6a3f4ebf273ef1,
0x3f80bf753f5cbf35,0x3f18bf463f67bf7b,0xbeac3dc93e16bec4,0xbf783f62bf3e3f0e,0xbf2c3ef1be790000,0xbf7d3f7fbf713f55,0xbedb3f22bf4e3f6d,0x3f04be953d493e48,
0x3d49be953f04bf35,0xbf4e3f22bedb3e48,0xbf713f7fbf7d3f6d,0xbe793ef1bf2c3f55,0xbf3e3f62bf783f80,0x3e163dc9beac3f0e,0x3f67bf463f18bec4,0x3f5cbf753f80bf7b,
0xbe60bd493ea1bf0e,0xbf773f5cbf313ef1,0x3f6fbf4e3f1dbec4,0x3f42bf673f7cbf7f,0xbf513f71bf7f3f7b,0x3dfb3e16becf3f22,0xbcc9be793efcbf35,0xbf653f3ebf093e95,
0xbf7a3f80bf733f55,0xbe893f04bf393f62,0x3eb8bf183f4abf6d,0xbf273edbbe2fbdc9,0x3f13beac3d973e48,0x3f7ebf7d3f6abf46,0xbf803f78bf5f3f35,0xbee63f2cbf583f75,
0x3f22bf553f75bf80,0xbef13e483dc9bec4,0xbf7f3f7bbf623f35,0xbe953f0ebf463f6d,0x3f46bf0e3e950000,0x3f62bf7b3f7fbf6d,0xbdc9be483ef1bf35,0xbf753f55bf223ec4,
0xbf463f0ebe958000,0xbf623f7bbf7f3f6d,0x3dc93e48bef13f35,0x3f75bf553f22bec4,0x3f22bf553f75bf80,0xbef13e483dc9bec4,0xbf7f3f7bbf623f35,0xbe953f0ebf463f6d,
0xbf6a3f3ebefc3e48,0xbf273f5cbf7a3f7f,0x3f7cbf7d3f65bf35,0x3dfbbedb3f31bf62,0x3cc9beac3f1dbf55,0xbf733f4ebf133e95,0x3f09be79bd973ec4,0x3f77bf803f6fbf46,
0xbecf3f2cbf5f3f7b,0x3f42bf043e603dc9,0xbe2fbe163ee6bf35,0xbf7e3f67bf393ef1,0xbf803f71bf4a3f0e,0xbea13f18bf513f75,0x3f58bf783f7fbf6d,0xbe89bd493eb8bf22,
0x3e793dc9bedb3f35,0x3f80bf753f4ebf0e,0x3e16bef13f3ebf6d,0xbf713f46bf043e48,0x3f5cbf223eac0000,0x3f2cbf623f7dbf7b,0xbf183e953d49bec4,0xbf673f7fbf783f55,
0x3f78bf7f3f67bf35,0xbd49be953f18bf55,0xbf7d3f62bf2c3ec4,0xbeac3f22bf5c3f7b,0x3f04bf463f71bf80,0xbf3e3ef1be16be48,0xbf4e3f75bf803f6d,0x3edbbdc9be793f0e,
0x3e89bf183f58bf7b,0xbf6f3f3ebee63dc9,0xbd973edbbf393f6d,0x3f7cbf5c3f1dbe95,0xbdfbbe793f13bf55,0xbf803f71bf423ef1,0x3ea13d49becf3f35,0x3f7abf7d3f5fbf22,
0xbf773f4ebf093e48,0xbeb83f2cbf653f7f,0x3f7fbf673f31bec4,0x3e2fbf043f4abf75,0xbf7e3f78bf513f0e,0x3cc93eacbf273f62,0x3f73bf803f6abf35,0xbe60be163efcbf46,
0xbec43f35bf6d3f80,0x3f6dbf353ec40000,0x3ec4bf353f6dbf80,0xbf6d3f35bec40000,0xbec43f35bf6d3f80,0x3f6dbf353ec40000,0x3ec4bf353f6dbf80,0xbf6d3f35bec40000,
0x3f6dbf353ec48000,0x3ec4bf353f6dbf80,0xbf6d3f35bec48000,0xbec43f35bf6d3f80,0x3f6dbf353ec48000,0x3ec4bf353f6dbf80,0xbf6d3f35bec48000,0xbec43f35bf6d3f80,
0x3f4abf783f7cbf55,0xbf313eac3d97bef1,0xbf653f80bf6f3f35,0x3f09be16be893f22,0x3efcbf4e3f7abf7b,0xbf6a3f2cbea1bdc9,0xbf273f67bf803f6d,0x3f51bf043dfb3e95,
0xbf1d3e793e2fbf0e,0xbf393f71bf7f3f62,0x3ee6bd49beb83f35,0x3f58bf7d3f77bf46,0xbf5f3f18be60be48,0xbecf3f3ebf733f7f,0x3f42bedb3cc93ec4,0x3f13bf5c3f7ebf75,
0xbf5c3f7fbf713f35,0x3f2cbe95be163f0e,0x3f18bf623f80bf6d,0xbf673f22be79be48,0xbf783f46bedb0000,0xbd493ef1bf4e3f7b,0x3f7dbf753f3ebec4,0xbeacbdc93f04bf55,
0x3f04bdc9beac3f35,0x3f3ebf753f7dbf55,0xbf4e3ef1bd49bec4,0xbedb3f46bf783f7b,0xbe793f22bf673f80,0x3f80bf623f18be48,0xbe16be953f2cbf6d,0xbf713f7fbf5c3f0e,
0x3f31bf713f7ebf55,0xbf653f18be2fbe95,0xbf7a3f78bf423ec4,0x3efcbd49becf3f46,0x3f6fbf2c3e893e48,0x3d97bf043f58bf7f,0xbf133e163ea1bf35,0xbf1d3f67bf803f62,
0xbf393eac3dfbbf0e,0xbee63f4ebf7c3f75,0x3e603e79bf273f6d,0x3f5fbf803f6abf22,0x3eb8bf3e3f77bf7b,0xbf7f3f5cbf093dc9,0xbf513f7dbf733f35,0x3f4abedbbcc93ef1,
0x3dc9bf0e3f62bf80,0xbf753f7bbf463ec4,0x3f22be48be953f35,0x3ef1bf553f7fbf6d,0xbf7f3f55bef10000,0x3e953e48bf223f6d,0x3f46bf7b3f75bf35,0xbf623f0ebdc9bec4,
0xbf7f3f55bef18000,0x3e953e48bf223f6d,0x3f46bf7b3f75bf35,0xbf623f0ebdc9bec4,0xbdc93f0ebf623f80,0x3f75bf7b3f46bec4,0xbf223e483e95bf35,0xbef13f55bf7f3f6d,
0x3e2f3eacbf423f7b,0x3f4abf7d3f6fbf22,0x3f39bf783f77bf35,0xbf733f2cbe60be95,0x3f58bf803f65bf0e,0xbf5f3f04bcc9bef1,0xbf6a3f18bdfbbec4,0x3d973edbbf513f7f,
0x3f7cbf713f27be48,0xbf1d3e163eb8bf46,0xbf313e793e89bf35,0xbea13f3ebf7a3f75,0xbf093d493ee6bf55,0xbefc3f5cbf803f62,0xbecf3f4ebf7e3f6d,0x3f7fbf673f13bdc9,
0xbf3e3e953e79bf35,0xbe163f22bf713f7b,0x3f67bf7f3f4ebec4,0xbf5c3ef13d49bf0e,0x3f80bf623f040000,0xbf183dc93edbbf55,0xbeac3f46bf7d3f6d,0x3f78bf753f2cbe48,
0xbf2c3f75bf783f35,0x3f7dbf463eac3e48,0xbedbbdc93f18bf6d,0xbf043f62bf803f55,0xbd49bef13f5cbf80,0xbf4e3f7fbf673f0e,0x3f71bf223e163ec4,0xbe79be953f3ebf7b,
0x3f73bf783f31be48,0xbf583edb3dfbbf22,0xbefcbd493f13bf6d,0xbeb83f4ebf7f3f62,0xbf423f7dbf6a3f0e,0x3f7cbf3e3e893e95,0x3f4abeacbe603f35,0xbcc9bf043f65bf7f,
0xbea1be793f39bf7b,0xbf093f67bf7e3f46,0xbf5f3f80bf513ec4,0x3f6fbf183d973ef1,0x3f27be16becf3f55,0x3e2fbf2c3f77bf75,0x3f1dbf713f7abf35,0xbf803f5cbee6bdc9,
0x3e483ec4bf553f80,0x3f0ebf6d3f7bbf35,0xbf7b3f6dbf0e0000,0x3f55bec4be483f35,0xbe48bec43f55bf80,0xbf0e3f6dbf7b3f35,0x3f7bbf6d3f0e0000,0xbf553ec43e48bf35,
0x3f7bbf6d3f0e8000,0xbf553ec43e48bf35,0x3e483ec4bf553f80,0x3f0ebf6d3f7bbf35,0xbf7b3f6dbf0e8000,0x3f55bec4be483f35,0xbe48bec43f55bf80,0xbf0e3f6dbf7b3f35,
0xbf733f18bcc9bf0e,0x3f093d49bf1d3f75,0xbefc3f67bf7c3f35,0x3f6fbf783f27bdc9,0x3f7fbf5c3ecf3e48,0xbf513eac3e89bf46,0x3dfbbf2c3f7abf6d,0xbf393f7dbf653ef1,
0xbea13f4ebf803f55,0x3f58bf803f4abe95,0x3f5fbedbbe2f3f35,0xbeb8be793f42bf7f,0xbd97bf043f6abf7b,0xbf133f71bf773f22,0xbf7e3f3ebe60bec4,0x3f31be16bee63f62,
0x3edbbf623f7dbf35,0xbf5c3f7fbf3e3e48,0x3f80bf463e793ec4,0xbf4e3e953eacbf55,0xbf713f75bf180000,0x3f78bf223d493f0e,0xbf2c3dc93f04bf6d,0x3e163ef1bf673f7b,
0xbf673ef13e16bf35,0x3f043dc9bf2c3f7b,0x3d49bf223f78bf6d,0xbf183f75bf713f0e,0x3eac3e95bf4e3f80,0x3e79bf463f80bf55,0xbf3e3f7fbf5c3ec4,0x3f7dbf623edb3e48,
0x3f7cbf2c3d973f0e,0xbf4a3e793ecfbf62,0x3f31bf7d3f5fbec4,0xbf733f71bf09bdc9,0xbe60bedb3f65bf7b,0xbe893f4ebf803f46,0xbf6f3f043dfbbf35,0x3f27bd49bf133f75,
0x3e2fbf3e3f7fbf55,0xbf1d3f78bf6a3ef1,0xbf393e163efcbf6d,0x3ea13eacbf583f7f,0xbf7a3f67bee6be48,0x3f77bf18bcc93f22,0xbeb83f5cbf7e3f35,0x3f42bf803f51be95,
0xbef1be483f46bf80,0x3dc93f0ebf753f6d,0x3e95bf553f7fbf35,0xbf223f7bbf623ec4,0x3f62bf7b3f220000,0xbf7f3f55be95bec4,0x3f75bf0ebdc93f35,0xbf463e483ef1bf6d,
0xbf623f7bbf228000,0x3f7fbf553e953ec4,0xbf753f0e3dc9bf35,0x3f46be48bef13f6d,0xbef1be483f46bf80,0x3dc93f0ebf753f6d,0x3e95bf553f7fbf35,0xbf223f7bbf623ec4,
0x3f39bf803f4abe48,0xbf653f78bf13bdc9,0x3e60bf4e3f7fbf35,0xbefc3f71bf6f3ef1,0x3f6abedbbe893f55,0xbf423e163f09bf75,0x3f7cbf5c3ea13ec4,0xbf7e3f2cbcc9bf22,
0xbf313d493f1dbf7b,0x3ee63e79bf513f7f,0xbf7a3f183d97bf35,0x3f5fbeacbeb83f62,0x3ecfbf673f77bf0e,0xbf273f7dbf583e95,0xbe2fbf043f73bf6d,0xbdfb3f3ebf803f46,
0x3f7dbf22bd493f35,0xbf713ef13e79bf55,0x3f5cbe95bedb3f6d,0xbf3e3dc93f18bf7b,0x3f4ebf7f3f2c0000,0xbf673f75bf04be48,0x3f78bf623eac3ec4,0xbf803f46be16bf0e,
0x3e16bf463f80bf35,0xbeac3f62bf783f0e,0x3f04bf753f67bec4,0xbf2c3f7fbf4e3e48,0xbf18bdc93f3ebf80,0x3edb3e95bf5c3f7b,0xbe79bef13f71bf6d,0x3d493f22bf7d3f55,
0x3f4abe16bf133f7b,0xbf393d493f27bf7f,0x3f65beacbecf3f6d,0xbf583e793efcbf75,0x3f77bf04be603f55,0xbf6f3edb3ea1bf62,0x3f7fbf2cbcc93f35,0xbf7c3f183dfbbf46,
0x3f1dbf7d3f51be48,0xbf313f80bf423dc9,0x3ee6bf713f6abec4,0xbf093f78bf5f3e95,0x3e89bf5c3f7abf0e,0xbeb83f67bf733ef1,0x3d97bf3e3f80bf35,0xbe2f3f4ebf7e3f22,
0x3f350000bf353f80,0xbf3500003f35bf80,0x3f350000bf353f80,0xbf3500003f35bf80,0x3f350000bf353f80,0xbf3500003f35bf80,0x3f350000bf353f80,0xbf3500003f35bf80,
0xbf353f80bf358000,0x3f35bf803f358000,0xbf353f80bf358000,0x3f35bf803f358000,0xbf353f80bf358000,0x3f35bf803f358000,0xbf353f80bf358000,0x3f35bf803f358000,
0x3f77be79bf7a3e48,0x3f6fbeacbf733e95,0x3f7fbd49bf800000,0x3f7cbe16bf7e3dc9,0x3f4abf18bf513f0e,0x3f39bf2cbf423f22,0x3f65bedbbf6a3ec4,0x3f58bf04bf5f3ef1,
0xbe89bf783e603f7b,0xbeb8bf713ea13f75,0xbd97bf803cc93f80,0xbe2fbf7d3dfb3f7f,0xbf1dbf4e3f133f55,0xbf31bf3e3f273f46,0xbee6bf673ecf3f6d,0xbf09bf5c3efc3f62,
0x3f4e3f22bf3ebf35,0x3f673ef1bf5cbf0e,0x3f783e95bf71bec4,0x3f803dc9bf7dbe48,0x3e163f7fbd49bf80,0x3eac3f75be79bf7b,0x3f043f62bedbbf6d,0x3f2c3f46bf18bf55,
0x3f18bf46bf2c3f35,0x3edbbf62bf043f55,0x3e79bf75beac3f6d,0x3d49bf7fbe163f7b,0x3f7dbdc9bf808000,0x3f71be95bf783e48,0x3f5cbef1bf673ec4,0x3f3ebf22bf4e3f0e,
0x3ecf3f71be89bf7b,0x3f273f4ebf09bf62,0xbe2f3f783ea1bf6d,0x3dfb3f803cc9bf7f,0xbf313f2c3f4abf0e,0xbee63f5c3f13bf46,0xbf7a3e163f7f0000,0xbf5f3edb3f6fbe95,
0x3f6abeacbf773e48,0x3f42bf18bf583ef1,0x3f7c3e79bf73bec4,0x3f7ebd49bf80bdc9,0x3f393f3ebf1dbf55,0x3f653f04bf51bf22,0x3e603f7dbd97bf80,0x3efc3f67beb8bf75,
0xbe95bf7b3dc93f80,0xbf22bf553ef13f6d,0xbf62bf0e3f463f35,0xbf7fbe483f753ec4,0xbf753e483f7f0000,0xbf463f0e3f62bec4,0xbef13f553f22bf35,0xbdc93f7b3e95bf6d,
0xbf753e483f7f8000,0xbf463f0e3f62bec4,0xbef13f553f22bf35,0xbdc93f7b3e95bf6d,0x3e953f7bbdc9bf80,0x3f223f55bef1bf6d,0x3f623f0ebf46bf35,0x3f7f3e48bf75bec4,
0x3e60bf71bee63f55,0xbe89bf7d3cc93f7f,0x3f6fbe79bf7e0000,0x3f27bf2cbf513ef1,0xbf7c3d493f7f3e48,0xbf4a3f043f6abe95,0xbf31bf4e3efc3f6d,0xbf73bedb3f583f22,
0xbf7abeac3f653f0e,0xbf773e163f803dc9,0xbeb8bf783dfb3f80,0xbf42bf3e3f133f62,0x3e2f3f803d97bf7b,0x3f1d3f5cbecfbf75,0xbf393f183f5fbec4,0xbea13f673f09bf46,
0x3eacbf62bf183f35,0xbe79bf7fbd493f7b,0xbf3ebf463f043f6d,0xbf7dbe953f673f0e,0x3edb3f75be16bf80,0x3f5c3f22bf2cbf55,0x3f803dc9bf78bec4,0x3f4ebef1bf713e48,
0xbf71bef13f4e3f35,0xbf783dc93f803e48,0xbf2c3f223f5cbec4,0xbe163f753edbbf55,0x3f67be95bf7d8000,0x3f04bf46bf3e3f0e,0xbd49bf7fbe793f6d,0xbf18bf623eac3f7b,
0x3d97bf78becf3f55,0xbf13bf673e893f7f,0x3f7e3d49bf7abec4,0x3f31bf18bf653e95,0x3ea13f7d3cc9bf7b,0x3f583f2cbf1dbf62,0xbf5f3eac3f7c0000,0xbeb83f5c3f27bf22,
0xbf7fbe793f6a3f0e,0xbf513edb3f77bdc9,0xbdfbbf80be603f6d,0xbf39bf4e3ee63f75,0x3f73be16bf80be48,0x3f09bf3ebf4a3ef1,0x3efc3f71be2fbf80,0x3f6f3f04bf42bf46,
0xbf0ebf6d3e483f80,0xbf7bbec43f553f35,0xbf553ec43f7b0000,0xbe483f6d3f0ebf35,0x3f0e3f6dbe48bf80,0x3f7b3ec4bf55bf35,0x3f55bec4bf7b0000,0x3e48bf6dbf0e3f35,
0xbf553ec43f7b8000,0xbe483f6d3f0ebf35,0x3f0e3f6dbe48bf80,0x3f7b3ec4bf55bf35,0x3f55bec4bf7b8000,0x3e48bf6dbf0e3f35,0xbf0ebf6d3e483f80,0xbf7bbec43f553f35,
0xbf42bf4e3ecf3f7b,0xbf7cbd493f773ef1,0x3f4abedbbf7a0000,0x3cc9bf78bee63f46,0x3f733f04bf39bf55,0x3f58beacbf7ebdc9,0xbefc3f3e3f51bec4,0x3eb83f7d3d97bf75,
0xbf273f183f6abe48,0x3e2f3f803e89bf62,0xbf1dbf673e603f80,0xbf80be793f653f22,0x3ea1bf5cbf313f0e,0xbf09bf713dfb3f7f,0x3f5f3f2cbf13bf6d,0x3f6fbe16bf7fbe95,
0xbf80be953f5c3f35,0xbf183f223f67be48,0x3eac3f7f3e16bf6d,0x3f783ef1bf3ebf55,0x3f2c3f62be79bf80,0x3f7d3dc9bf71bf0e,0x3edbbf46bf4e3ec4,0xbf04bf753d493f7b,
0xbd493f753f04bf35,0x3f4e3f46bedbbf7b,0x3f71bdc9bf7dbec4,0x3e79bf62bf2c3f0e,0x3f3ebef1bf788000,0xbe16bf7fbeac3f55,0xbf67bf223f183f6d,0xbf5c3e953f803e48,
0xbf093f2c3f65be48,0x3efc3f783cc9bf75,0xbecfbf7dbdfb3f6d,0xbf7fbeac3f513f46,0x3f7c3edbbf42bf55,0x3f1dbf18bf6f3dc9,0xbf313f043f770000,0x3ea13f803e60bf62,
0x3f583f3ebee6bf7b,0x3f5fbe79bf80be95,0xbf6a3e163f7e3ec4,0xbd973f713f13bf22,0x3e2fbf67bf273f0e,0xbf4abf4e3eb83f7f,0x3f393f5cbe89bf80,0x3f73bd49bf7abef1,
0xbf46bf553e953f80,0xbf623e483f7f3ec4,0x3dc93f7b3ef1bf35,0x3f753f0ebf22bf6d,0x3f22bf0ebf750000,0xbef1bf7bbdc93f6d,0xbf7fbe483f623f35,0xbe953f553f46bec4,
0xbf223f0e3f758000,0x3ef13f7b3dc9bf6d,0x3f7f3e48bf62bf35,0x3e95bf55bf463ec4,0xbf46bf553e953f80,0xbf623e483f7f3ec4,0x3dc93f7b3ef1bf35,0x3f753f0ebf22bf6d,
0xbf6f3d493f773f0e,0x3d973f783f09bf22,0x3f13bf18bf730000,0xbf1dbf713cc93f75,0xbf31bf673dfb3f7b,0xbf653e163f7c3ef1,0x3f7a3f04bf27bf6d,0x3efcbf2cbf6a3dc9,
0x3eb83f803e89bf55,0x3f7f3e79bf58bf46,0xbf51bf4e3ea13f80,0xbf4a3eac3f803e95,0xbf393edb3f7e3e48,0x3ee63f7d3e2fbf62,0x3e60bf5cbf423ec4,0xbf5fbf3e3ecf3f7f,
0x3e793f7f3edbbf35,0x3f803e95bf4ebf55,0x3e16bf62bf3e3ec4,0xbf71bf223f043f7b,0x3f5c3f46beacbf80,0x3f2cbef1bf7dbe48,0xbf18bf75bd493f6d,0xbf673dc93f783f0e,
0x3f783dc9bf67bf35,0xbd49bf75bf183f0e,0xbf7dbef13f2c3f6d,0xbeac3f463f5cbe48,0x3f04bf22bf718000,0xbf3ebf623e163f7b,0xbf4e3e953f803ec4,0x3edb3f7f3e79bf55,
0x3f5fbe16bf7abf0e,0xbecfbf80bea13f46,0xbf423eac3f803ec4,0x3f133f783dfbbf62,0x3f1dbf04bf7cbe48,0xbf39bf673d973f75,0xbee63f2c3f6f0000,0x3f583f4ebe89bf7f,
0xbefcbf7dbe603f55,0xbf6a3d493f733f22,0x3f273f713cc9bf6d,0x3f51be79bf7ebef1,0xbf4abf5c3e2f3f7b,0xbf313edb3f7f3e95,0x3f653f3ebeb8bf80,0x3f09bf18bf77bdc9,
0xbf6dbf353ec43f80,0xbec43f353f6d0000,0x3f6d3f35bec4bf80,0x3ec4bf35bf6d0000,0xbf6dbf353ec43f80,0xbec43f353f6d0000,0x3f6d3f35bec4bf80,0x3ec4bf35bf6d0000,
0xbec43f353f6d8000,0x3f6d3f35bec4bf80,0x3ec4bf35bf6d8000,0xbf6dbf353ec43f80,0xbec43f353f6d8000,0x3f6d3f35bec4bf80,0x3ec4bf35bf6d8000,0xbf6dbf353ec43f80,
0xbdfb3f5c3f51be48,0x3f803edbbf27bf75,0x3ea1bf3ebf6a0000,0xbf7abf183efc3f7f,0x3e893f7d3f09bf0e,0x3f6f3d49bf65bf46,0xbd97bf71bf313ec4,0xbf7cbe793f4a3f62,
0x3f7e3f04bf13bf7b,0x3cc9bf67bf423e95,0xbf73bf2c3ecf3f80,0xbe603f4e3f5fbdc9,0x3f773e16bf58bf55,0xbeb8bf80bee63f22,0xbf7fbeac3f393f6d,0x3e2f3f783f1dbef1,
0x3f5cbdc9bf71bf35,0xbf2cbf75be163f55,0xbf183ef13f803ec4,0x3f673f46be79bf7b,0x3f783f22bedbbf80,0x3d49bf62bf4e3e48,0xbf7dbe953f3e3f6d,0x3eac3f7f3f04bf0e,
0xbf04bf7fbeac3f35,0xbf3e3e953f7d3f0e,0x3f4e3f62bd49bf6d,0x3edbbf22bf78be48,0x3e79bf46bf678000,0xbf80bef13f183f7b,0x3e163f753f2cbec4,0x3f713dc9bf5cbf55,
0xbf80bedb3f1d3f7b,0x3ea13f7d3f13bef1,0x3f583f5cbd97bf6d,0x3e89bf3ebf6fbdc9,0xbecfbf80befc3f0e,0xbf423e793f7a3f22,0xbe2f3f4e3f650000,0x3f7e3eacbf31bf75,
0x3cc93f673f4abe48,0x3f733e16bf51bf62,0x3f09bf04bf7fbec4,0xbf77bf2c3eb83f7f,0xbf6abd493f5f3f55,0x3f273f783e60bf46,0x3f7c3f18bee6bf80,0xbdfbbf71bf393e95,
0xbf7fbf0e3ef13f80,0x3e953f7b3f22bec4,0x3f46be48bf75bf35,0xbf62bf553dc93f6d,0xbdc93f553f620000,0x3f753e48bf46bf6d,0xbf22bf7bbe953f35,0xbef13f0e3f7f3ec4,
0xbdc93f553f628000,0x3f753e48bf46bf6d,0xbf22bf7bbe953f35,0xbef13f0e3f7f3ec4,0x3f7f3f0ebef1bf80,0xbe95bf7bbf223ec4,0xbf463e483f753f35,0x3f623f55bdc9bf6d,
0x3f513f673d97bf55,0x3dfbbf4ebf6abdc9,0x3cc9bf5cbf5f0000,0xbf65bd493f583f62,0x3e60bf3ebf73be48,0xbf77be793f393f75,0xbf6fbe163f4a3f6d,0x3f423f713e2fbf46,
0x3f13bedbbf7fbf0e,0xbf7ebf183ecf3f7f,0xbf80bf043efc3f80,0x3ee63f803f09bef1,0xbf7abf2c3ea13f7b,0x3e893f783f31be95,0x3eb83f7d3f1dbec4,0x3f27beacbf7cbf22,
0xbf3ebf75be793f35,0xbe163f463f713e48,0x3f673dc9bf4ebf6d,0xbf5cbf62bd493f55,0x3f803ef1bf04bf80,0xbf18bf7fbedb3f0e,0xbeac3f223f7d3ec4,0x3f783e95bf2cbf7b,
0xbf2c3e953f783f35,0x3f7d3f22beacbf7b,0xbedbbf7fbf183ec4,0xbf043ef13f803f0e,0xbd49bf62bf5c8000,0xbf4e3dc93f673f55,0x3f713f46be16bf6d,0xbe79bf75bf3e3e48,
0x3f653f5c3cc9bf55,0xbe60bf71bf4a3dc9,0x3e89bf2cbf7cbec4,0xbf6abe163f423f75,0xbf7fbf183eb83f7b,0x3f133f803efcbef1,0x3dfb3f673f580000,0x3f31be79bf73bf46,
0x3ee6bf04bf80bf0e,0xbf7abeac3f1d3f7f,0xbf77bf3e3e2f3f6d,0x3ecf3f7d3f27be95,0xbd973f4e3f6f3e48,0x3f51bd49bf5fbf62,0x3f7e3edbbf09bf80,0xbf39bf78bea13f22,
0xbf7bbec43f0e3f80,0x3f553f6d3e48bf35,0xbe48bf6dbf550000,0xbf0e3ec43f7b3f35,0x3f7b3ec4bf0ebf80,0xbf55bf6dbe483f35,0x3e483f6d3f550000,0x3f0ebec4bf7bbf35,
0x3e483f6d3f558000,0x3f0ebec4bf7bbf35,0xbf7bbec43f0e3f80,0x3f553f6d3e48bf35,0xbe48bf6dbf558000,0xbf0e3ec43f7b3f35,0x3f7b3ec4bf0ebf80,0xbf55bf6dbe483f35,
0x3f653e16bf39bf7b,0xbf7abf3e3dfb3f62,0xbe89bf71bf510000,0xbecf3f043f7f3f22,0xbf273e793f6f3f55,0x3f7c3edbbefcbf7f,0x3f1d3f803f09bec4,0x3cc9bf4ebf73be95,
0xbee6bf7dbf313e48,0xbe603f2c3f7e3ef1,0xbf77beac3f133f80,0x3f6a3f5c3d97bf46,0x3f423f783eb8bf0e,0xbe2fbf67bf5fbdc9,0x3f4abd49bf58bf6d,0xbf80bf183ea13f75,
0xbedb3ef13f7d3f35,0x3f5c3dc9bf3ebf7b,0xbf80bf223e793f6d,0x3f4e3f753eacbf0e,0x3f713e95bf18bf80,0xbf78bf463d493f55,0x3f2c3f7f3f04bec4,0xbe16bf62bf67be48,
0x3f673f623e16bf35,0xbf04bf7fbf2c3e48,0xbd493f463f783ec4,0x3f18be95bf71bf55,0xbeacbf75bf4e8000,0xbe793f223f803f0e,0x3f3ebdc9bf5cbf6d,0xbf7dbef13edb3f7b,
0xbf13bf80bf273e48,0x3dfb3f5c3f6f3e95,0xbf80bf183e893f6d,0x3f653f673e60bf22,0xbf093eac3f733f55,0x3f5f3e16bf31bf7f,0x3ecf3f783f4a0000,0x3d97bf3ebf7cbef1,
0xbf51bd493f423f7b,0x3f7e3f04beb8bf75,0x3cc93f4e3f773ec4,0x3ee6bedbbf7abf46,0x3f583f713ea1bf0e,0xbefcbf7dbf393dc9,0x3f6a3e79bf1dbf80,0xbf7fbf2c3e2f3f62,
0xbf62be483f223f80,0x3f7f3f0ebe95bf6d,0xbf75bf55bdc93f35,0x3f463f7b3ef1bec4,0xbef1bf7bbf460000,0x3dc93f553f753ec4,0x3e95bf0ebf7fbf35,0xbf223e483f623f6d,
0x3ef13f7b3f468000,0xbdc9bf55bf75bec4,0xbe953f0e3f7f3f35,0x3f22be48bf62bf6d,0xbf62be483f223f80,0x3f7f3f0ebe95bf6d,0xbf75bf55bdc93f35,0x3f463f7b3ef1bec4,
0x3cc9bf3ebf7ebf0e,0xbea13f043f7c3f46,0xbf09bf7dbf420000,0x3e893f673f6a3e95,0x3f6f3eacbefcbf7b,0xbf7fbf183e603f62,0x3f13be79bf65bf6d,0xbf4abd493f393f7f,
0xbf80bf2c3dfb3f55,0x3f733f5c3e2fbf22,0xbf58be163f273f80,0x3f773edbbecfbf75,0xbeb8bf71bf5fbe48,0x3d973f4e3f7a3ef1,0xbf51bf78bee63ec4,0x3f1d3f803f31bdc9,
0x3f7d3f463d49bf35,0xbf71bf62be793f0e,0x3f5c3f753edbbec4,0xbf3ebf7fbf183e48,0x3f4e3dc9bf2cbf80,0xbf67be953f043f7b,0x3f783ef1beacbf6d,0xbf80bf223e163f55,
0x3e16bf22bf80bf35,0xbeac3ef13f783f55,0x3f04be95bf67bf6d,0xbf2c3dc93f4e3f7b,0xbf18bf7fbf3e8000,0x3edb3f753f5c3e48,0xbe79bf62bf71bec4,0x3d493f463f7d3f0e,
0x3dfb3f4e3f7c3f0e,0xbcc9bf3ebf7fbf22,0x3ea13f673f6f3ec4,0xbe60bf5cbf77bef1,0x3efc3f783f583e48,0xbecfbf71bf65be95,0x3f273f803f390000,0xbf13bf7dbf4abdc9,
0x3f7e3f18be2fbf55,0xbf80bf2c3d973f46,0x3f733edbbeb8bf6d,0xbf7abf043e893f62,0x3f5f3e79bf09bf7b,0xbf6abeac3ee63f75,0x3f423d49bf31bf80,0xbf51be163f1d3f7f,
0x3f350000bf353f80,0xbf3500003f35bf80,0x3f350000bf353f80,0xbf3500003f35bf80,0x3f350000bf353f80,0xbf3500003f35bf80,0x3f350000bf353f80,0xbf3500003f35bf80,
0xbf353f80bf358000,0x3f35bf803f358000,0xbf353f80bf358000,0x3f35bf803f358000,0xbf353f80bf358000,0x3f35bf803f358000,0xbf353f80bf358000,0x3f35bf803f358000,
0x3efcbf5cbf093f55,0x3ecfbf67bee63f62,0x3f27bf3ebf313f35,0x3f13bf4ebf1d3f46,0x3dfbbf7dbe2f3f7b,0x3cc9bf80bd973f7f,0x3ea1bf71beb83f6d,0x3e60bf78be893f75,
0xbf5fbf043f583f0e,0xbf6abedb3f653ef1,0xbf42bf2c3f393f35,0xbf51bf183f4a3f22,0xbf7ebe163f7c3e48,0xbf80bd493f7f3dc9,0xbf73beac3f6f3ec4,0xbf7abe793f773e95,
0x3f18bf46bf2c3f35,0x3edbbf62bf043f55,0x3e79bf75beac3f6d,0x3d49bf7fbe163f7b,0x3f7dbdc9bf800000,0x3f71be95bf783e48,0x3f5cbef1bf673ec4,0x3f3ebf22bf4e3f0e,
0xbf4ebf223f3e3f35,0xbf67bef13f5c3f0e,0xbf78be953f713ec4,0xbf80bdc93f7d3e48,0xbe16bf7f3d493f80,0xbeacbf753e793f7b,0xbf04bf623edb3f6d,0xbf2cbf463f183f55,
0x3eb8bf67befc3f55,0x3d97bf7dbe603f75,0x3f51bf04bf653ec4,0x3f1dbf3ebf393f22,0x3f803d49bf7ebe48,0x3f73be79bf7c3dc9,0x3f583f18bf42bf35,0x3f773eacbf6abef1,
0xbf6fbedb3f5f3f0e,0xbf7fbe163f7a3e95,0xbf13bf5c3ee63f6d,0xbf4abf2c3f313f46,0xbcc9bf80bdfb3f7b,0xbea1bf783e2f3f7f,0x3f09bf4ebf273f35,0x3e89bf71becf3f62,
0x3e953f7bbdc9bf80,0x3f223f55bef1bf6d,0x3f623f0ebf46bf35,0x3f7f3e48bf75bec4,0x3f75be48bf7f0000,0x3f46bf0ebf623ec4,0x3ef1bf55bf223f35,0x3dc9bf7bbe953f6d,
0x3f75be48bf7f8000,0x3f46bf0ebf623ec4,0x3ef1bf55bf223f35,0x3dc9bf7bbe953f6d,0xbe95bf7b3dc93f80,0xbf22bf553ef13f6d,0xbf62bf0e3f463f35,0xbf7fbe483f753ec4,
0x3f093f67bea1bf7b,0x3f5f3f18bf39bf46,0xbecf3f5c3f1dbf35,0x3d973f803e2fbf75,0x3f13bf3ebf423f0e,0x3dfbbf78beb83f62,0x3f803e16bf77bec4,0x3f65beacbf7a3dc9,
0x3f58bedbbf733e48,0x3efcbf4ebf313f22,0x3f6a3f04bf4abf35,0x3f7f3d49bf7cbe95,0xbf51bf2c3f273f55,0xbf7ebe793f6f3ef1,0x3cc9bf7dbe893f6d,0xbee6bf713e603f7f,
0x3f713ef1bf4ebf35,0x3f78bdc9bf80be48,0x3f2cbf22bf5c3ec4,0x3e16bf75bedb3f55,0xbf673e953f7d0000,0xbf043f463f3ebf0e,0x3d493f7f3e79bf6d,0x3f183f62beacbf7b,
0x3eacbf62bf183f35,0xbe79bf7fbd493f7b,0xbf3ebf463f043f6d,0xbf7dbe953f673f0e,0x3edb3f75be16bf80,0x3f5c3f22bf2cbf55,0x3f803dc9bf78bec4,0x3f4ebef1bf713e48,
0x3f42bf04bf6f3e48,0x3e2fbf71befc3f46,0x3f4a3f3ebf09bf6d,0x3f803e16bf73bef1,0xbee63f4e3f39bf0e,0x3e603f803dfbbf75,0xbf77bedb3f513f35,0xbf6a3e793f7f3dc9,
0xbf27bf5c3eb83f7b,0xbf7cbeac3f5f3f22,0x3f1dbf2cbf583ec4,0xbcc9bf7dbea13f62,0x3f653f18bf31bf55,0x3f7abd49bf7ebe95,0xbe893f673f13bf35,0x3ecf3f78bd97bf7f,
0xbf0ebf6d3e483f80,0xbf7bbec43f553f35,0xbf553ec43f7b0000,0xbe483f6d3f0ebf35,0x3f0e3f6dbe48bf80,0x3f7b3ec4bf55bf35,0x3f55bec4bf7b0000,0x3e48bf6dbf0e3f35,
0xbf553ec43f7b8000,0xbe483f6d3f0ebf35,0x3f0e3f6dbe48bf80,0x3f7b3ec4bf55bf35,0x3f55bec4bf7b8000,0x3e48bf6dbf0e3f35,0xbf0ebf6d3e483f80,0xbf7bbec43f553f35,
0xbf7fbe163f6f3f0e,0xbf133f2c3f5fbe95,0x3dfbbf71bf093f35,0xbf31bf5c3ea13f7f,0x3f65be79bf80be48,0x3e60bf67bf1d3f22,0x3e893f803e2fbf6d,0x3f6a3f18bf27bf62,
0x3d973f7d3eb8bf55,0x3f513f3ebefcbf75,0xbf7ebeac3f583f35,0xbf393f043f73bdc9,0xbee6bf783cc93f7b,0xbf7abedb3f4a3f46,0x3f77bd49bf7cbec4,0x3ecfbf4ebf423ef1,
0xbd493f753f04bf35,0x3f4e3f46bedbbf7b,0x3f71bdc9bf7dbec4,0x3e79bf62bf2c3f0e,0x3f3ebef1bf780000,0xbe16bf7fbeac3f55,0xbf67bf223f183f6d,0xbf5c3e953f803e48,
0x3f803e95bf5cbf35,0x3f18bf22bf673e48,0xbeacbf7fbe163f6d,0xbf78bef13f3e3f55,0xbf2cbf623e793f80,0xbf7dbdc93f713f0e,0xbedb3f463f4ebec4,0x3f043f75bd49bf7b,
0x3f7a3d49bf73bf0e,0x3e89bf5cbf393ef1,0xbeb83f4e3f4abec4,0x3f273f67be2fbf7f,0xbf13bf713d973f7b,0xbf7ebe163f6a3f22,0x3f803e79bf5fbf35,0x3ee6bf3ebf583e95,
0xbe60bf80bea13f55,0xbf77bf043f313f62,0x3f6f3f18bf1dbf6d,0x3f42bedbbf7cbdc9,0xbf513eac3f7f3e48,0x3dfb3f7d3ecfbf46,0xbcc9bf78befc3f35,0xbf65bf2c3f093f75,
0x3f463f55be95bf80,0x3f62be48bf7fbec4,0xbdc9bf7bbef13f35,0xbf75bf0e3f223f6d,0xbf223f0e3f750000,0x3ef13f7b3dc9bf6d,0x3f7f3e48bf62bf35,0x3e95bf55bf463ec4,
0x3f22bf0ebf758000,0xbef1bf7bbdc93f6d,0xbf7fbe483f623f35,0xbe953f553f46bec4,0x3f463f55be95bf80,0x3f62be48bf7fbec4,0xbdc9bf7bbef13f35,0xbf75bf0e3f223f6d,
0x3ecfbf3ebf5f3e48,0xbf42bf5c3e603f7f,0x3e2f3f7d3ee6bf35,0x3f7e3edbbf39bf62,0x3f803eacbf4abf55,0x3ea1bf4ebf513e95,0xbf583e793f7f3ec4,0x3e893f803eb8bf46,
0xbf6abf2c3efc3f7b,0xbf273f043f7a3dc9,0x3f7c3e16bf65bf35,0x3dfbbf67bf313ef1,0x3cc9bf71bf1d3f0e,0xbf73bf183f133f75,0x3f093f783d97bf6d,0x3f773d49bf6fbf22,
0xbf78bdc93f673f35,0x3d493f753f18bf0e,0x3f7d3ef1bf2cbf6d,0x3eacbf46bf5c3e48,0xbf043f223f710000,0x3f3e3f62be16bf7b,0x3f4ebe95bf80bec4,0xbedbbf7fbe793f55,
0x3e793f7f3edbbf35,0x3f803e95bf4ebf55,0x3e16bf62bf3e3ec4,0xbf71bf223f043f7b,0x3f5c3f46beacbf80,0x3f2cbef1bf7dbe48,0xbf18bf75bd493f6d,0xbf673dc93f783f0e,
0x3f773f18bf09bf7b,0x3eb8bf3ebf653dc9,0xbf7fbedb3f313f6d,0xbe2f3f5c3f4abe95,0x3f7e3e79bf51bf55,0xbcc9bf71bf273ef1,0xbf73bd493f6a3f35,0x3e603f7d3efcbf22,
0x3e89bf4ebf583e48,0xbf6fbf2c3ee63f7f,0xbd973f673f39bec4,0x3f7c3f04bf1dbf75,0xbdfbbf78bf133f0e,0xbf80beac3f423f62,0x3ea13f803ecfbf35,0x3f7a3e16bf5fbf46,
0xbf6dbf353ec43f80,0xbec43f353f6d0000,0x3f6d3f35bec4bf80,0x3ec4bf35bf6d0000,0xbf6dbf353ec43f80,0xbec43f353f6d0000,0x3f6d3f35bec4bf80,0x3ec4bf35bf6d0000,
0xbec43f353f6d8000,0x3f6d3f35bec4bf80,0x3ec4bf35bf6d8000,0xbf6dbf353ec43f80,0xbec43f353f6d8000,0x3f6d3f35bec4bf80,0x3ec4bf35bf6d8000,0xbf6dbf353ec43f80,
0x3f1d3f783e2fbf55,0x3f39beacbf7fbef1,0xbee6bf80beb83f35,0xbf583e163f773f22,0x3f5f3f4ebe60bf7b,0x3ecfbf2cbf73bdc9,0xbf42bf673cc93f6d,0xbf133f043f7e3e95,
0x3f4abe79bf7cbf0e,0xbf31bf71bd973f62,0xbf653d493f6f3f35,0x3f093f7d3e89bf46,0x3efcbf18bf7abe48,0xbf6abf3e3ea13f7f,0xbf273edb3f803ec4,0x3f513f5cbdfbbf75,
0xbf04bf7fbeac3f35,0xbf3e3e953f7d3f0e,0x3f4e3f62bd49bf6d,0x3edbbf22bf78be48,0x3e79bf46bf670000,0xbf80bef13f183f7b,0x3e163f753f2cbec4,0x3f713dc9bf5cbf55,
0xbf5c3dc93f713f35,0x3f2c3f753e16bf55,0x3f18bef1bf80bec4,0xbf67bf463e793f7b,0xbf78bf223edb3f80,0xbd493f623f4ebe48,0x3f7d3e95bf3ebf6d,0xbeacbf7fbf043f0e,
0x3f393f713dfbbf55,0x3ee6bf18bf7cbe95,0xbe60bf78bf273ec4,0xbf5f3d493f6a3f46,0xbeb83f2c3f773e48,0x3f7f3f04bf09bf7f,0x3f51be16bf73bf35,0xbf4abf67bcc93f62,
0x3f31beacbf7ebf0e,0xbf65bf4e3e2f3f75,0xbf7abe793f423f6d,0x3efc3f803ecfbf22,0x3f6f3f3ebe89bf7b,0x3d97bf5cbf583dc9,0xbf13bf7dbea13f35,0xbf1d3edb3f803ef1,
0x3f7f3f0ebef1bf80,0xbe95bf7bbf223ec4,0xbf463e483f753f35,0x3f623f55bdc9bf6d,0x3dc9bf55bf620000,0xbf75be483f463f6d,0x3f223f7b3e95bf35,0x3ef1bf0ebf7fbec4,
0x3dc9bf55bf628000,0xbf75be483f463f6d,0x3f223f7b3e95bf35,0x3ef1bf0ebf7fbec4,0xbf7fbf0e3ef13f80,0x3e953f7b3f22bec4,0x3f46be48bf75bf35,0xbf62bf553dc93f6d,
0xbf7cbeac3f273f7b,0x3f1d3f7d3eb8bf22,0x3f313f783e89bf35,0x3ea1bf2cbf7abe95,0x3f093f803ee6bf0e,0x3efcbf04bf80bef1,0x3ecfbf18bf7ebec4,0xbf7fbedb3f133f7f,
0x3e2f3f713f42be48,0x3f4abe16bf6fbf46,0x3f39be79bf77bf35,0xbf73bf3e3e603f75,0x3f58bd49bf65bf55,0xbf5fbf5c3cc93f62,0xbf6abf4e3dfb3f6d,0x3d973f673f51bdc9,
0x3f2cbe95bf78bf35,0xbf7dbf223eac3f7b,0x3edb3f7f3f18bec4,0x3f04bef1bf80bf0e,0x3d493f623f5c0000,0x3f4ebdc9bf67bf55,0xbf71bf463e163f6d,0x3e793f753f3ebe48,
0xbf3ebf75be793f35,0xbe163f463f713e48,0x3f673dc9bf4ebf6d,0xbf5cbf62bd493f55,0x3f803ef1bf04bf80,0xbf18bf7fbedb3f0e,0xbeac3f223f7d3ec4,0x3f783e95bf2cbf7b,
0x3ea13f783f39be48,0x3f09bedbbf7ebf22,0x3f5f3d49bf51bf6d,0xbf6fbf4e3d973f62,0xbf27bf7dbecf3f0e,0xbe2f3f3e3f773e95,0xbf1d3eac3f7a3f35,0x3f803f04bee6bf7f,
0x3f733e79bf31bf7b,0xbf58bf67bdfb3f46,0xbefcbf80bf133ec4,0xbeb83f183f7f3ef1,0xbf423e163f6a3f55,0x3f7c3f2cbe89bf75,0x3f4a3f713e60bf35,0xbcc9bf5cbf65bdc9,
0xbf7bbec43f0e3f80,0x3f553f6d3e48bf35,0xbe48bf6dbf550000,0xbf0e3ec43f7b3f35,0x3f7b3ec4bf0ebf80,0xbf55bf6dbe483f35,0x3e483f6d3f550000,0x3f0ebec4bf7bbf35,
0x3e483f6d3f558000,0x3f0ebec4bf7bbf35,0xbf7bbec43f0e3f80,0x3f553f6d3e48bf35,0xbe48bf6dbf558000,0xbf0e3ec43f7b3f35,0x3f7b3ec4bf0ebf80,0xbf55bf6dbe483f35,
0x3ea1bf18bf80bf0e,0xbf58bd493f4a3f75,0xbf5fbf67be2f3f35,0x3eb83f783f42bdc9,0x3d973f5c3f6a3e48,0x3f13beacbf77bf46,0x3f7e3f2cbe60bf6d,0xbf31bf7dbee63ef1,
0xbf73bf4e3cc93f55,0x3f093f803f1dbe95,0xbefc3edb3f7c3f35,0x3f6f3e79bf27bf7f,0x3f7f3f04becfbf7b,0xbf51bf71be893f22,0x3dfbbf3ebf7abec4,0xbf393e163f653f62,
0x3f673f623e16bf35,0xbf04bf7fbf2c3e48,0xbd493f463f783ec4,0x3f18be95bf71bf55,0xbeacbf75bf4e0000,0xbe793f223f803f0e,0x3f3ebdc9bf5cbf6d,0xbf7dbef13edb3f7b,
0x3edbbef1bf7dbf35,0xbf5cbdc93f3e3f7b,0x3f803f22be79bf6d,0xbf4ebf75beac3f0e,0xbf71be953f183f80,0x3f783f46bd49bf55,0xbf2cbf7fbf043ec4,0x3e163f623f673e48,
0xbe2f3f2c3f7f3f0e,0x3f1dbe79bf6abf62,0x3f393f7d3efcbec4,0xbea1bf71bf58bdc9,0x3f7a3edbbee6bf7b,0xbf77bf4ebcc93f46,0x3eb8bf04bf7ebf35,0xbf423d493f513f75,
0x3f7c3f3ebd97bf55,0xbf4abf78becf3ef1,0x3f31be16bf5fbf6d,0xbf73beac3f093f7f,0xbe60bf67bf65be48,0xbe893f183f803f22,0xbf6fbf5cbdfb3f35,0x3f273f803f13be95,
0x3f623e48bf22bf80,0xbf7fbf0e3e953f6d,0x3f753f553dc9bf35,0xbf46bf7bbef13ec4,0x3ef13f7b3f460000,0xbdc9bf55bf75bec4,0xbe953f0e3f7f3f35,0x3f22be48bf62bf6d,
0xbef1bf7bbf468000,0x3dc93f553f753ec4,0x3e95bf0ebf7fbf35,0xbf223e483f623f6d,0x3f623e48bf22bf80,0xbf7fbf0e3e953f6d,0x3f753f553dc9bf35,0xbf46bf7bbef13ec4,
0x3f313f803f1dbe48,0xbee6bf78bf51bdc9,0x3f7a3f4e3d97bf35,0xbf5fbf71beb83ef1,0xbecf3edb3f773f55,0x3f27be16bf58bf75,0x3e2f3f5c3f733ec4,0x3dfbbf2cbf80bf22,
0x3f39bd49bf4abf7b,0xbf65be793f133f7f,0x3e60bf18bf7fbf35,0xbefc3eac3f6f3f62,0x3f6a3f673e89bf0e,0xbf42bf7dbf093e95,0x3f7c3f04bea1bf6d,0xbf7ebf3e3cc93f46,
0xbe163f223f803f35,0x3eacbef1bf78bf55,0xbf043e953f673f6d,0x3f2cbdc9bf4ebf7b,0x3f183f7f3f3e0000,0xbedbbf75bf5cbe48,0x3e793f623f713ec4,0xbd49bf46bf7dbf0e,
0x3f7d3f463d49bf35,0xbf71bf62be793f0e,0x3f5c3f753edbbec4,0xbf3ebf7fbf183e48,0x3f4e3dc9bf2cbf80,0xbf67be953f043f7b,0x3f783ef1beacbf6d,0xbf80bf223e163f55,
0xbf1d3e163f513f7b,0x3f31bd49bf42bf7f,0xbee63eac3f6a3f6d,0x3f09be79bf5fbf75,0xbe893f043f7a3f55,0x3eb8bedbbf73bf62,0xbd973f2c3f803f35,0x3e2fbf18bf7ebf46,
0x3f4a3f7d3f13be48,0xbf39bf80bf273dc9,0x3f653f713ecfbec4,0xbf58bf78befc3e95,0x3f773f5c3e60bf0e,0xbf6fbf67bea13ef1,0x3f7f3f3e3cc9bf35,0xbf7cbf4ebdfb3f22,
};
__device__ __align__(1024) uint8_t g_hT[32 * 262144];
__device__ __align__(1024) bf16 g_U[128 * 2 * 8 * 1024];
__device__ __align__(128) float2 g_gate[2048];
__device__ __align__(16) uint4 g_agg[16 * 512];
#define CS 32
__device__ __align__(128) unsigned g_cnt[8 * 32];
constexpr int CNT_U = 0, CNT_V = 1, CNT_H = 2  , CNT_DONE = 4, CNT_EPOCH = 5, CNT_G = 6;
#define PROFK(i) do { } while (0)
#define PROFC(i) do { } while (0)
#define PROF(i) do { } while (0)
#define PROFX(i) do { } while (0)
#define PROFS(i) do { } while (0)
#define PROFG(i) do { } while (0)

constexpr int SLOT = 32768;
constexpr int OFF_HS = 4 * SLOT;
constexpr int OFF_W = OFF_HS + 16384;
constexpr int OFF_T = OFF_HS + 28672;
constexpr int OFF_F = OFF_W + 2 * 18432;
constexpr int OFF_G = OFF_F + 8192;
constexpr int OFF_K = OFF_G + 1024;
constexpr int OFF_U = 6 * SLOT;
constexpr int OFF_BAR = OFF_U + 32768;
constexpr int OFF_GS = OFF_BAR + 320;
constexpr int OFF_SC = OFF_GS + 128;
constexpr int OFF_KEPT = OFF_SC + 512;
constexpr int OFF_PROF = OFF_KEPT + 64;
constexpr int SMEM_BYTES = OFF_PROF;
constexpr int BAR_FULL = 0  , BAR_X = 10, BAR_U = 11, BAR_W = 12, BAR_T = 13, BAR_F = 14  ,
              BAR_EMPTY = 17  , BAR_HW = 22  , BAR_WR = 26, BAR_VW = 27, BAR_S1 = 28, BAR_CD = 29,
              BAR_C = 30  , BAR_HR = 32, BAR_HD = 33  ;

#define DEVI __device__ __forceinline__
constexpr unsigned SPIN_LIMIT = 1u << 22;

DEVI uint32_t smem_u32(const void* p) { return (uint32_t)__cvta_generic_to_shared(p); }
DEVI uint64_t gtime() { uint64_t t; asm volatile("mov.u64 %0, %%globaltimer;" : "=l"(t)); return t; }
DEVI void mbar_init(uint32_t bar, uint32_t cnt) { asm volatile("mbarrier.init.shared::cta.b64 [%0], %1;" :: "r"(bar), "r"(cnt) : "memory"); }
DEVI void mbar_expect_tx(uint32_t bar, uint32_t bytes) { asm volatile("mbarrier.arrive.expect_tx.shared::cta.b64 _, [%0], %1;" :: "r"(bar), "r"(bytes) : "memory"); }
DEVI void mbar_arrive(uint32_t bar) { asm volatile("mbarrier.arrive.shared::cta.b64 _, [%0];" :: "r"(bar) : "memory"); }
DEVI void mbar_wait(uint32_t bar, uint32_t parity) {
    asm volatile("{\n.reg .pred p;\n.reg .u32 n;\nmov.u32 n, 0;\n"
                 "LW:\nmbarrier.try_wait.parity.shared::cta.b64 p, [%0], %1;\n@p bra LD;\n"
                 "add.u32 n, n, 1;\nsetp.lt.u32 p, n, %2;\n@p bra LW;\nLD:\n}"
                 :: "r"(bar), "r"(parity), "n"(1 << 17) : "memory");
}
DEVI bool elect() {
    uint32_t p;
    asm volatile("{\n.reg .pred P;\nelect.sync _|P, 0xffffffff;\nselp.u32 %0, 1, 0, P;\n}" : "=r"(p));
    return p;
}
DEVI void fence_barrier_init() { asm volatile("fence.mbarrier_init.release.cluster;" ::: "memory"); }
DEVI void fence_proxy_async_smem() { asm volatile("fence.proxy.async.shared::cta;" ::: "memory"); }
DEVI void helper_sync() { asm volatile("bar.sync 1, 128;" ::: "memory"); }

DEVI void pause(unsigned n) {
    asm volatile("{\n.reg .pred p;\n.reg .u32 a, b;\nmov.u32 a, %%clock;\n"
                 "LP:\nmov.u32 b, %%clock;\nsub.u32 b, b, a;\nsetp.lt.u32 p, b, %0;\n@p bra LP;\n}" :: "r"(n) : "memory");
}
#define P_POLL 0
#define NPOLL 1
DEVI void wait_counter(const unsigned* p, unsigned target) {
    unsigned v[NPOLL];
    auto ld = [&](int i) { asm volatile("ld.relaxed.gpu.global.u32 %0, [%1];" : "=r"(v[i]) : "l"(p) : "memory"); };
#pragma unroll
    for (int i = 0; i < NPOLL; i++) { if (i) pause(200); ld(i); }
#pragma unroll 1
    for (unsigned n = 0; n < SPIN_LIMIT; n++) {
#pragma unroll
        for (int i = 0; i < NPOLL; i++) {
            if ((int)(v[i] - target) >= 0) return;
            if (P_POLL) pause(P_POLL);
            ld(i);
        }
    }
}
DEVI void signal_counter(unsigned* p) {
    asm volatile("red.relaxed.gpu.global.add.u32 [%0], 1;" :: "l"(p) : "memory");
}

DEVI void tma_load_3d(uint32_t dst, const CUtensorMap* map, uint32_t bar, int c0, int c1, int c2) {
    asm volatile("cp.async.bulk.tensor.3d.shared::cluster.global.mbarrier::complete_tx::bytes [%0], [%1, {%3, %4, %5}], [%2];"
        :: "r"(dst), "l"(map), "r"(bar), "r"(c0), "r"(c1), "r"(c2) : "memory");
}
DEVI void tma_load_4d(uint32_t dst, const CUtensorMap* map, uint32_t bar, int c0, int c1, int c2, int c3) {
    asm volatile("cp.async.bulk.tensor.4d.shared::cluster.global.mbarrier::complete_tx::bytes [%0], [%1, {%3, %4, %5, %6}], [%2];"
        :: "r"(dst), "l"(map), "r"(bar), "r"(c0), "r"(c1), "r"(c2), "r"(c3) : "memory");
}
DEVI void tma_store_5d(const CUtensorMap* map, uint32_t src, int c0, int c4) {
    asm volatile("cp.async.bulk.tensor.5d.global.shared::cta.bulk_group [%0, {%2, %4, %4, %4, %3}], [%1];"
        :: "l"(map), "r"(src), "r"(c0), "r"(c4), "r"(0) : "memory");
}
DEVI void tma_store_4d(const CUtensorMap* map, uint32_t src, int c0, int c1, int c2, int c3) {
    asm volatile("cp.async.bulk.tensor.4d.global.shared::cta.bulk_group [%0, {%2, %3, %4, %5}], [%1];"
        :: "l"(map), "r"(src), "r"(c0), "r"(c1), "r"(c2), "r"(c3) : "memory");
}
DEVI void bulk_load(uint32_t dst, const void* src, uint32_t bytes, uint32_t bar) {
    asm volatile("cp.async.bulk.shared::cluster.global.mbarrier::complete_tx::bytes [%0], [%1], %2, [%3];"
        :: "r"(dst), "l"(src), "r"(bytes), "r"(bar) : "memory");
}
DEVI void bulk_prefetch_l2(const void* src, uint32_t bytes) {
    asm volatile("cp.async.bulk.prefetch.L2.global [%0], %1;" :: "l"(src), "r"(bytes) : "memory");
}
DEVI void tma_store_3d(const CUtensorMap* map, uint32_t src, int c0, int c1, int c2) {
    asm volatile("cp.async.bulk.tensor.3d.global.shared::cta.bulk_group [%0, {%2, %3, %4}], [%1];"
        :: "l"(map), "r"(src), "r"(c0), "r"(c1), "r"(c2) : "memory");
}
DEVI void bulk_store(void* dst, uint32_t src, uint32_t bytes) {
    asm volatile("cp.async.bulk.global.shared::cta.bulk_group [%0], [%1], %2;" :: "l"(dst), "r"(src), "r"(bytes) : "memory");
}
DEVI void bulk_commit() { asm volatile("cp.async.bulk.commit_group;" ::: "memory"); }
DEVI void bulk_wait0() { asm volatile("cp.async.bulk.wait_group 0;" ::: "memory"); }

DEVI void wgmma_fence() { asm volatile("wgmma.fence.sync.aligned;" ::: "memory"); }
DEVI void wgmma_commit() { asm volatile("wgmma.commit_group.sync.aligned;" ::: "memory"); }
template<int N> DEVI void wgmma_wait() { asm volatile("wgmma.wait_group.sync.aligned %0;" :: "n"(N) : "memory"); }
template<int N> DEVI void wgmma_wait_all(float (&d)[N]) {
    wgmma_wait<0>();
#pragma unroll
    for (int i = 0; i < N; i++) asm volatile("" : "+f"(d[i]) :: "memory");
}
template<int R> DEVI void reg_alloc() { asm volatile("setmaxnreg.inc.sync.aligned.u32 %0;" :: "n"(R)); }
template<int R> DEVI void reg_dealloc() { asm volatile("setmaxnreg.dec.sync.aligned.u32 %0;" :: "n"(R)); }

DEVI uint64_t make_desc(uint32_t addr, uint32_t lbo, uint32_t sbo, uint32_t mode = 1) {
    return (uint64_t)(((addr & 0x3FFFF) >> 4) | ((lbo >> 4) << 16)) | ((uint64_t)((sbo >> 4) | (mode << 30)) << 32);
}

#define ACC8(a, o) "+f"(a[o+0]), "+f"(a[o+1]), "+f"(a[o+2]), "+f"(a[o+3]), "+f"(a[o+4]), "+f"(a[o+5]), "+f"(a[o+6]), "+f"(a[o+7])
#define OUT8(a, o) "=f"(a[o+0]), "=f"(a[o+1]), "=f"(a[o+2]), "=f"(a[o+3]), "=f"(a[o+4]), "=f"(a[o+5]), "=f"(a[o+6]), "=f"(a[o+7])
#define ACC32(a, o) ACC8(a, o), ACC8(a, o+8), ACC8(a, o+16), ACC8(a, o+24)

template<int TA, int TB>
DEVI void wgmma_n128(float (&d)[64], uint64_t da, uint64_t db, int scale_d) {
    asm volatile("{\n.reg .pred p;\nsetp.ne.b32 p, %66, 0;\n"
        "wgmma.mma_async.sync.aligned.m64n128k16.f32.bf16.bf16 "
        "{%0, %1, %2, %3, %4, %5, %6, %7, %8, %9, %10, %11, %12, %13, %14, %15, "
        "%16, %17, %18, %19, %20, %21, %22, %23, %24, %25, %26, %27, %28, %29, %30, %31, "
        "%32, %33, %34, %35, %36, %37, %38, %39, %40, %41, %42, %43, %44, %45, %46, %47, "
        "%48, %49, %50, %51, %52, %53, %54, %55, %56, %57, %58, %59, %60, %61, %62, %63}, "
        "%64, %65, p, 1, 1, %67, %68;\n}\n"
        : ACC32(d, 0), ACC32(d, 32)
        : "l"(da), "l"(db), "r"(scale_d), "n"(TA), "n"(TB));
}
#define SS_N16 "{\n.reg .pred p;\nsetp.ne.b32 p, 0, 0;\n" \
        "wgmma.mma_async.sync.aligned.m64n16k16.f32.bf16.bf16 " \
        "{%0, %1, %2, %3, %4, %5, %6, %7}, %8, %9, p, 1, 1, %10, 0;\n}\n"
template<int TA> DEVI void wgmma_n16(float* d, uint64_t da, uint64_t db) {
    asm volatile(SS_N16 : OUT8(d, 0) : "l"(da), "l"(db), "n"(TA));
}
#define RS_N64 "{\n.reg .pred p;\nsetp.ne.b32 p, %37, 0;\n" \
        "wgmma.mma_async.sync.aligned.m64n64k16.f32.bf16.bf16 " \
        "{%0, %1, %2, %3, %4, %5, %6, %7, %8, %9, %10, %11, %12, %13, %14, %15, " \
        "%16, %17, %18, %19, %20, %21, %22, %23, %24, %25, %26, %27, %28, %29, %30, %31}, " \
        "{%32, %33, %34, %35}, %36, p, 1, 1, %38;\n}\n"
template<int SCALE_D, int TB = 0>
DEVI void wgmma_rs_n64(float (&d)[32], const uint32_t (&a)[4], uint64_t db) {
    if (SCALE_D) asm volatile(RS_N64 : ACC32(d, 0) : "r"(a[0]), "r"(a[1]), "r"(a[2]), "r"(a[3]), "l"(db), "n"(1), "n"(TB));
    else asm volatile(RS_N64 : OUT8(d, 0), OUT8(d, 8), OUT8(d, 16), OUT8(d, 24) : "r"(a[0]), "r"(a[1]), "r"(a[2]), "r"(a[3]), "l"(db), "n"(0), "n"(TB));
}
DEVI void ldsm_x4_t(uint32_t (&r)[4], uint32_t addr) {
    asm volatile("ldmatrix.sync.aligned.m8n8.x4.trans.shared.b16 {%0, %1, %2, %3}, [%4];"
        : "=r"(r[0]), "=r"(r[1]), "=r"(r[2]), "=r"(r[3]) : "r"(addr) : "memory");
}
DEVI void ldsm_x4(uint32_t (&r)[4], uint32_t addr) {
    asm volatile("ldmatrix.sync.aligned.m8n8.x4.shared.b16 {%0, %1, %2, %3}, [%4];"
        : "=r"(r[0]), "=r"(r[1]), "=r"(r[2]), "=r"(r[3]) : "r"(addr) : "memory");
}
DEVI void stsm_x4(uint32_t addr, uint32_t r0, uint32_t r1, uint32_t r2, uint32_t r3) {
    asm volatile("stmatrix.sync.aligned.m8n8.x4.shared.b16 [%0], {%1, %2, %3, %4};"
        :: "r"(addr), "r"(r0), "r"(r1), "r"(r2), "r"(r3) : "memory");
}
DEVI void stsm_x4_t(uint32_t addr, uint32_t r0, uint32_t r1, uint32_t r2, uint32_t r3) {
    asm volatile("stmatrix.sync.aligned.m8n8.x4.trans.shared.b16 [%0], {%1, %2, %3, %4};"
        :: "r"(addr), "r"(r0), "r"(r1), "r"(r2), "r"(r3) : "memory");
}
DEVI uint32_t movm(uint32_t a) { uint32_t d; asm volatile("movmatrix.sync.aligned.m8n8.trans.b16 %0, %1;" : "=r"(d) : "r"(a)); return d; }
DEVI uint32_t pack2(float lo, float hi) { uint32_t d; asm("cvt.rn.bf16x2.f32 %0, %1, %2;" : "=r"(d) : "f"(hi), "f"(lo)); return d; }
DEVI float bf_lo(uint32_t v) { return __uint_as_float(v << 16); }
DEVI float bf_hi(uint32_t v) { return __uint_as_float(v & 0xffff0000u); }
DEVI float bf_round(float v) { return __bfloat162float(__float2bfloat16_rn(v)); }
DEVI uint32_t bf_mul2(uint32_t a, uint32_t b) { uint32_t d; asm("mul.rn.bf16x2 %0, %1, %2;" : "=r"(d) : "r"(a), "r"(b)); return d; }
DEVI uint32_t bf_add2(uint32_t a, uint32_t b) { uint32_t d; asm("add.rn.bf16x2 %0, %1, %2;" : "=r"(d) : "r"(a), "r"(b)); return d; }
DEVI uint32_t bf_sub2(uint32_t a, uint32_t b) { uint32_t d; asm("sub.rn.bf16x2 %0, %1, %2;" : "=r"(d) : "r"(a), "r"(b)); return d; }
DEVI uint4 lds128u(uint32_t a) { uint4 v; asm volatile("ld.shared.v4.u32 {%0, %1, %2, %3}, [%4];" : "=r"(v.x), "=r"(v.y), "=r"(v.z), "=r"(v.w) : "r"(a) : "memory"); return v; }
DEVI void sts128u(uint32_t a, uint32_t x, uint32_t y, uint32_t z, uint32_t w) { asm volatile("st.shared.v4.u32 [%0], {%1, %2, %3, %4};" :: "r"(a), "r"(x), "r"(y), "r"(z), "r"(w) : "memory"); }
DEVI uint2 lds64u(uint32_t a) { uint2 v; asm volatile("ld.shared.v2.u32 {%0, %1}, [%2];" : "=r"(v.x), "=r"(v.y) : "r"(a) : "memory"); return v; }
DEVI uint32_t ldg32u(const void* p) { uint32_t v; asm volatile("ld.global.nc.u32 %0, [%1];" : "=r"(v) : "l"(p) : "memory"); return v; }
DEVI void sts64(uint32_t a, float x, float y) { asm volatile("st.shared.v2.f32 [%0], {%1, %2};" :: "r"(a), "f"(x), "f"(y) : "memory"); }
DEVI void sts32(uint32_t a, uint32_t v) { asm volatile("st.shared.u32 [%0], %1;" :: "r"(a), "r"(v) : "memory"); }
DEVI uint32_t lds16(uint32_t a) { uint32_t v; asm volatile("ld.shared.u16 %0, [%1];" : "=r"(v) : "r"(a) : "memory"); return v; }
DEVI void cmul2(uint32_t& x, uint32_t& y, uint32_t c, uint32_t s) {
    asm("{\n.reg .b32 t, u;\nxor.b32 t, %3, 0x80008000;\nmul.rn.bf16x2 t, %1, t;\nmul.rn.bf16x2 u, %1, %2;\n"
        "fma.rn.bf16x2 %1, %0, %3, u;\nfma.rn.bf16x2 %0, %0, %2, t;\n}" : "+r"(x), "+r"(y) : "r"(c), "r"(s));
}
DEVI void cmul2c(uint32_t& x, uint32_t& y, uint32_t c, uint32_t s) {
    asm("{\n.reg .b32 t, u, n;\nxor.b32 n, %3, 0x80008000;\nmul.rn.bf16x2 t, %1, %3;\nmul.rn.bf16x2 u, %1, %2;\n"
        "fma.rn.bf16x2 %1, %0, n, u;\nfma.rn.bf16x2 %0, %0, %2, t;\n}" : "+r"(x), "+r"(y) : "r"(c), "r"(s));
}
DEVI void sts16(uint32_t a, float v) { asm volatile("st.shared.u16 [%0], %1;" :: "r"(a), "r"(pack2(v, v)) : "memory"); }

DEVI float2 cmul(float2 a, float2 b) { return make_float2(fmaf(a.x, b.x, -a.y * b.y), fmaf(a.x, b.y, a.y * b.x)); }
DEVI float2 cfma(float2 a, float2 b, float2 c) { return make_float2(fmaf(a.x, b.x, fmaf(-a.y, b.y, c.x)), fmaf(a.x, b.y, fmaf(a.y, b.x, c.y))); }

struct Params {
    const bf16 *lam_re, *lam_im, *log_dt, *dskip, *gate_w, *c_re, *c_im, *b_re, *b_im, *x;
    int swapB;
};

#define R8_POLL 8
#define R8B 1
#define SCB 32
#define C0 1
#define R8L 8
template<int R8N, class F> DEVI void radix8(uint32_t sb, uint32_t gtab, int w, int lane, int bar, F mid) {
    const uint64_t dg = make_desc(gtab, 128, 256, 0);
    const uint32_t st = sb + OFF_U + (lane >> 4) * 16384 + (lane & 7) * 128 + (((2 * w + ((lane >> 3) & 1)) ^ (lane & 7)) << 4);
    float acc[2][8 * R8N];
    const uint64_t da = make_desc(sb + OFF_U, 16, 16384);
    constexpr int NB = 16 / R8N;
#pragma unroll
    for (int i = 0; i <= NB; i++) {
        if (i < NB) {
            wgmma_fence();
#pragma unroll
            for (int j = 0; j < R8N; j++) wgmma_n16<1>(acc[i & 1] + 8 * j, da + 64 * (R8N * i + j), dg);
            wgmma_commit();
        }
        if (i * R8N == R8_POLL) mid();
        if (i) {
            float* a = acc[~i & 1];
            if (i < NB) wgmma_wait<1>(); else wgmma_wait<0>();
#pragma unroll
            for (int j = 0; j < 8 * R8N; j++) asm volatile("" : "+f"(a[j]) :: "memory");
            if (R8N > 2 || ((R8N * (i - 1)) & 2)) asm volatile("bar.sync %0, 128;" :: "r"(bar) : "memory");
#pragma unroll
            for (int j = 0; j < R8N; j++) {
                const int c = R8N * (i - 1) + j;
                stsm_x4_t((st ^ ((c & 3) << 4)) + c * 1024,
                          pack2(a[8 * j], a[8 * j + 1]), pack2(a[8 * j + 2], a[8 * j + 3]), pack2(a[8 * j + 4], a[8 * j + 5]), pack2(a[8 * j + 6], a[8 * j + 7]));
            }
        }
    }
}

template<int N> DEVI void c_take(float (&acc)[32], uint32_t (&p)[16]) {
    wgmma_wait<N>();
#pragma unroll
    for (int i = 0; i < 32; i++) asm volatile("" : "+f"(acc[i]) :: "memory");
#pragma unroll
    for (int i = 0; i < 16; i++) p[i] = pack2(acc[2 * i], acc[2 * i + 1]);
}
DEVI void c_mm4(float (&acc)[32], const uint32_t (&a)[4][4], uint64_t df) {
    wgmma_rs_n64<0>(acc, a[0], df);
    wgmma_rs_n64<1>(acc, a[1], df + 2);
    wgmma_rs_n64<1>(acc, a[2], df + 4);
    wgmma_rs_n64<1>(acc, a[3], df + 6);
    wgmma_commit();
}
template<int H> DEVI void c_mm2(float (&acc)[2][32], const uint32_t (&a)[2][2][4], uint64_t df) {
    wgmma_fence();
#pragma unroll
    for (int i = 0; i < 2; i++) {
        wgmma_rs_n64<H>(acc[i], a[i][0], df + 2 * H);
        wgmma_rs_n64<1>(acc[i], a[i][1], df + 2 * H + 4);
        wgmma_commit();
    }
}
DEVI void c_twiddle(uint32_t (&p)[16], uint32_t (&a)[2][2][4], const uint4* tw) {
#pragma unroll
    for (int jp = 0; jp < 2; jp++)
#pragma unroll
        for (int hh = 0; hh < 2; hh++) {
            const uint4 w = tw[hh * 2 + jp];
#pragma unroll
            for (int jl = 0; jl < 2; jl++) {
                const int o = 4 * jp + 2 * jl + hh;
                cmul2(p[o], p[8 + o], jl ? w.z : w.x, jl ? w.w : w.y);
                a[jp][0][2 * hh + jl] = movm(p[o]);
                a[jp][1][2 * hh + jl] = movm(p[8 + o]);
            }
        }
}
template<bool LW> DEVI void c_stage(float (&acc)[2][32], const uint4 (&tw)[8], uint64_t df, uint32_t (&w)[2][4][4], uint32_t wa, uint32_t wm) {
    uint32_t p[16], a0[2][2][4], a1[2][2][4];
    c_take<1>(acc[0], p);
    c_twiddle(p, a0, tw);
    c_take<0>(acc[1], p);
    if (LW) {
#pragma unroll
        for (int j = 0; j < 4; j++) ldsm_x4_t(w[0][j], (j < 2 ? wa : wm) + (j & 1) * 512);
    }
    c_mm2<0>(acc, a0, df);
    c_twiddle(p, a1, tw + 4);
    if (LW) {
#pragma unroll
        for (int j = 0; j < 4; j++) ldsm_x4_t(w[1][j], ((j < 2 ? wa : wm) ^ 32) + (j & 1) * 512);
    }
    c_mm2<1>(acc, a1, df);
}

DEVI void phase_c(uint32_t sb, int warp, int mrow, int lane, const uint4 (&tw)[8]) {
    PROFC(0);
    const uint64_t df = make_desc(sb + OFF_F, 16, 1024);
    float acc[2][32];
    uint32_t w[2][4][4];
    const uint32_t xa = sb + OFF_U + ((lane >> 4) * 4 + ((lane & 7) >> 1)) * 1024 + warp * 128
                      + ((((lane & 1) * 4 + ((lane >> 3) & 1)) ^ warp ^ ((lane >> 1) & 3)) << 4);
    const uint32_t wo = sb + OFF_W + (~warp & 1) * 18432 + (lane >> 4) * 9216 + (lane & 7) * 64 + ((((lane >> 3) & 1) ^ ((lane >> 1) & 3)) << 4);
    const uint32_t wa = wo + (warp >> 1) * 1152, wm = wo + 4608 + mrow * 1152;
    {
        uint32_t a[2][4][4];
#pragma unroll
        for (int h = 0; h < 2; h++)
#pragma unroll
            for (int s = 0; s < 4; s++) ldsm_x4_t(a[h][s], (xa ^ (h * 32)) + (s & 1) * 8192 + (s >> 1) * 16384);
        wgmma_fence();
        c_mm4(acc[0], a[0], df);
        c_mm4(acc[1], a[1], df);
    }
    PROFC(1);
    c_stage<true>(acc, tw, df, w, wa, wm);
    PROFC(2);
#pragma unroll
    for (int h = 0; h < 2; h++) {
        uint32_t p[16], a[4][4];
        c_take<1>(acc[h], p);
#pragma unroll
        for (int j = 0; j < 4; j++)
#pragma unroll
            for (int hh = 0; hh < 2; hh++) {
                if (j < 2) cmul2(p[2 * j + hh], p[8 + 2 * j + hh], w[h][j][hh], w[h][j][2 + hh]);
                else cmul2c(p[2 * j + hh], p[8 + 2 * j + hh], w[h][j][hh], w[h][j][2 + hh]);
                a[j >> 1][2 * (j & 1) + hh] = p[8 + 2 * j + hh];
                a[2 + (j >> 1)][2 * (j & 1) + hh] = p[2 * j + hh];
            }
        wgmma_fence();
        c_mm4(acc[h], a, df);
    }
    PROFC(3);
    c_stage<false>(acc, tw, df, w, wa, wm);
    PROFC(4);
#pragma unroll
    for (int h = 0; h < 2; h++) {
        uint32_t p[16];
        if (h) c_take<0>(acc[1], p); else c_take<1>(acc[0], p);
#pragma unroll
        for (int s = 0; s < 4; s++)
            stsm_x4_t((xa ^ (h * 32)) + (s & 1) * 8192 + ((s >> 1) ^ 1) * 16384, p[4 * s], p[4 * s + 1], p[4 * s + 2], p[4 * s + 3]);
    }
    PROFC(5);
}

#define PACE_V 250
#define VPOS 27
#define PACE_H 200
#define T_W0 2000
#define T_XS 1500
#define D_XS 0
#define P_XS 500
#define T_G 0
#define T_BA 1000
#define T_W1 3000
#define P_W 0
#define P_XE 300
#define P_R0 0
#define POL2 0
#define T_B2 4000
#define T_W 5000
#define PACE_U 200
#define PACE_L 0
#define T_FA 0
#define REG_M 216
#define REG_H 72
#define NS 4
#define SLOT_OF(k) (((k) + 1) % 4)
DEVI void tma_prefetch_4d(const CUtensorMap* map, int c0, int c1, int c2, int c3) {
    asm volatile("cp.async.bulk.prefetch.tensor.4d.L2.global [%0, {%1, %2, %3, %4}];" :: "l"(map), "r"(c0), "r"(c1), "r"(c2), "r"(c3) : "memory");
}
DEVI void bar_sync(int id, int n) { asm volatile("bar.sync %0, %1;" :: "r"(id), "r"(n) : "memory"); }
DEVI void bar_arrive(int id, int n) { asm volatile("bar.arrive %0, %1;" :: "r"(id), "r"(n) : "memory"); }
DEVI uint4 ldg128(const void* p) { uint4 v; asm volatile("ld.global.nc.v4.u32 {%0, %1, %2, %3}, [%4];" : "=r"(v.x), "=r"(v.y), "=r"(v.z), "=r"(v.w) : "l"(p)); return v; }
DEVI uint32_t ldg16(const void* p) { uint32_t v; asm volatile("ld.global.nc.u16 %0, [%1];" : "=r"(v) : "l"(p)); return v; }
DEVI uint32_t bf_fma2(uint32_t a, uint32_t b, uint32_t c) { uint32_t d; asm("fma.rn.bf16x2 %0, %1, %2, %3;" : "=r"(d) : "r"(a), "r"(b), "r"(c)); return d; }
DEVI void bulk_wait_read() { asm volatile("cp.async.bulk.wait_group.read 0;" ::: "memory"); }

DEVI float lds32f(uint32_t a) { float v; asm volatile("ld.shared.f32 %0, [%1];" : "=f"(v) : "r"(a) : "memory"); return v; }
DEVI uint32_t mbar_test(uint32_t bar, uint32_t parity) {
    uint32_t ok;
    asm volatile("{\n.reg .pred p;\nmbarrier.test_wait.parity.shared::cta.b64 p, [%1], %2;\nselp.u32 %0, 1, 0, p;\n}" : "=r"(ok) : "r"(bar), "r"(parity) : "memory");
    return ok;
}
template<int TA> DEVI void ring_steps(float (&acc)[2][64], uint32_t sb, uint32_t fb, int n, int ns, int& s, uint32_t& phm, bool first, bool lead, int first_bar, int last_bar, int pi) {
    const uint64_t da0 = TA ? make_desc(sb, 4096, 512, 2) : make_desc(sb, 16, 1024), db0 = make_desc(sb + 16384, 16, 1024);
    uint32_t eb = sb + OFF_BAR + 8 * BAR_HR;
    mbar_wait(fb + 8 * s, (phm >> s) & 1);
    if (first_bar) bar_sync(first_bar, 256);
#pragma unroll 1
    for (;;) {
        PROFK(pi++);
        const uint64_t da = da0 + (uint32_t)(s * 2048), db = db0 + (uint32_t)(s * 2048);
        wgmma_fence();
#pragma unroll
        for (int j = 0; j < 4; j++) {
            wgmma_n128<TA, 0>(acc[0], da + (TA ? 64 : 2) * j, db + 2 * j, j || !first);
            wgmma_n128<TA, 0>(acc[1], da + 512 + (TA ? 64 : 2) * j, db + 2 * j, j || !first);
        }
        wgmma_commit();
        first = false;
        phm ^= 1u << s;
        if (--n == 0) break;
        const uint32_t en = sb + OFF_BAR + 8 * BAR_EMPTY + 8 * s;
        if (++s == ns) s = 0;
        const uint32_t ok = mbar_test(fb + 8 * s, (phm >> s) & 1);
        wgmma_wait<1>();
        if (lead) mbar_arrive(eb);
        eb = en;
        if (!ok) mbar_wait(fb + 8 * s, (phm >> s) & 1);
        __syncwarp();
    }
    if (last_bar) bar_arrive(last_bar, 256);
    wgmma_wait<1>();
    if (lead) mbar_arrive(eb);
}

__global__ void __cluster_dims__(2, 1, 1) __launch_bounds__(384, 1)
fused_kernel(const __grid_constant__ CUtensorMap mapB, const __grid_constant__ CUtensorMap mapX,
             const __grid_constant__ CUtensorMap mapXs, const __grid_constant__ CUtensorMap mapU0,
             const __grid_constant__ CUtensorMap mapU2, const __grid_constant__ CUtensorMap mapXe,
             const __grid_constant__ CUtensorMap mapCre, const __grid_constant__ CUtensorMap mapCim,
             const __grid_constant__ CUtensorMap mapV, const __grid_constant__ CUtensorMap mapO,
             const __grid_constant__ CUtensorMap mapWr, const __grid_constant__ CUtensorMap mapWi,
             const __grid_constant__ CUtensorMap mapH,
             const __grid_constant__ Params P) {
    extern __shared__ __align__(1024) uint8_t sm[];
    const uint32_t sb = smem_u32(sm);
    const uint32_t bars = sb + OFF_BAR;
    const unsigned cl = blockIdx.x >> 1;
    const int role = cl < 4 ? 32 + 8 * cl : cl < 36 ? ((cl - 4) & 24) + ((cl - 5) & 7) : cl < 64 ? 33 + (cl - 36) / 7 * 8 + (cl - 30) % 7 : cl;
    const int b = role * 2 + (blockIdx.x & 1), tid = threadIdx.x, warp = __shfl_sync(0xffffffffu, tid >> 5, 0), lane = tid & 31;
    const bool main_cta = b < 128;
    if (b == 129) return;
    const int rp = (b >> 1) & 3, mq = ((b >> 3) & 2) + (b & 1), dt = ((b >> 1) & 4) + (b >> 5), tc = 4 * rp + mq;
    const int cls = b == 128 ? 128 : (b & 31) ? (b & 31) + 64 * (b >> 5) : (b == 64 ? 32 : b == 32 ? 64 : b);
    auto load_g1 = [&](int k, int s) {
        const uint32_t full = bars + 8 * (BAR_FULL + s + (k >> 4) * 5), st = sb + s * SLOT;
        mbar_expect_tx(full, SLOT);
        tma_load_4d(st, &mapB, full, (k & 15) * 64, 0, 0, dt * 8 + (k >> 4) * 64);
        tma_load_4d(st + 16384, &mapX, full, (k & 15) * 64, 0, 0, tc * 64);
    };
    if (warp != 8 && elect()) {
        if (warp == 11) PROFG(0);
        const int u = warp - (warp > 8);
        asm volatile("prefetch.tensormap [%0];" :: "l"(&mapB + 2 + u) : "memory");
        if (u != BAR_X - 5) mbar_init(bars + 8 * (5 + u), 1);
        mbar_init(bars + 8 * (16 + u), u ? 4 : 1);
        if (u < 8) mbar_init(bars + 8 * (27 + u), u < 2 ? 4 : u < 3 ? 8 : u < 5 ? 64 : 1);
        fence_barrier_init();
        fence_proxy_async_smem();
    }
    __syncwarp();
    const bool real_cls = (cls & 127) == 0;
    const int t = tid & 127;
    auto load_epoch = [&]() {
        unsigned e;
        asm volatile("ld.relaxed.gpu.global.u32 %0, [%1];" : "=r"(e) : "l"(&g_cnt[CNT_EPOCH * CS]));
        return e + 1;
    };
    const int g = lane >> 2, q = lane & 3;

    if (warp < 8) {
        reg_alloc<REG_M>();
        const int wg = warp >> 2, w = warp & 3;
        if (tid == 0) PROFX(94);
        bar_sync(0, 384);
        if (tid == 224) PROFG(8);
        auto kept = [&](int i) { uint64_t v; asm volatile("ld.volatile.shared.u64 %0, [%1];" : "=l"(v) : "r"(sb + OFF_KEPT + 8 * i) : "memory"); return v; };
        const uint32_t fb = bars + 8 * (BAR_FULL + 5 * wg);
        uint32_t phm = 0;
        if (wg) {
            {
                const int pp = (dt * 64 + 8 * (t & 64) + (t & 63)) & 1023;
                const uint32_t lr_ = ldg16(P.lam_re + pp), li_ = ldg16(P.lam_im + pp), ld_ = ldg16(P.log_dt + pp);
                const unsigned epoch = load_epoch();
                if (t < 64 && tc < 15 && main_cta) g_agg[tc * 512 + (dt + (t >> 5) * 8) * 32 + lane] = make_uint4(0u, 0u, 0u, 0u);
                if (t < 5) asm volatile("st.shared.u64 [%0], %1;" :: "r"(sb + OFF_KEPT + 8 * lane),
                    "l"(lane == 0 ? (P.swapB ? 255ull : 127ull) | ((uint64_t)epoch << 32) : lane == 1 ? (uint64_t)g_agg : lane == 2 ? (uint64_t)(c_tab + 10240) : lane == 3 ? (uint64_t)&mapB : (uint64_t)g_hT) : "memory");
                const float lr = bf_lo(lr_), li = bf_lo(li_);
                const float dl = bf_round(expf(bf_lo(ld_)));
                const float mag = expf(dl * lr);
                float sn, cs; sincospif(dl * li * 0.31830988618379067f, &sn, &cs);
                const float2 l1 = make_float2(mag * cs, mag * sn);
                const float inv = 1.f / (lr * lr + li * li);
                const float2 cf = cmul(make_float2(l1.x - 1.f, l1.y), make_float2(lr * inv, -li * inv));
                sts128u(sb + OFF_K + 16 * t, __float_as_uint(l1.x), __float_as_uint(P.swapB ? -l1.y : l1.y), __float_as_uint(cf.x), __float_as_uint(cf.y));
                if (tid == 128) PROFX(92);
            }
            {
                const int kk = (t >> 3) & 7, r = t & 7;
                float sn, cs;
                sincospif((float)(((cls + 256 * kk) * r) & 2047) * (1.f / 1024.f), &sn, &cs);
                sn *= 1.f / 1024.f; cs *= 1.f / 1024.f;
                const uint32_t gf = sb + OFF_G + kk * 16 + r * 2, gi = sb + OFF_G + 512 + r * 16 + kk * 2;
                if (t < 64) {
                    sts16(gf, cs); sts16(gf + 128, real_cls ? 0.f : sn); sts16(gf + 256, -sn); sts16(gf + 384, real_cls ? 0.f : cs);
                    sts16(gi, cs); sts16(gi + 128, -sn); sts16(gi + 256, sn); sts16(gi + 384, cs);
                }
            }
            if (main_cta) {
                uint32_t fa[16][4];
                pause(T_FA);
#pragma unroll
                for (int i = 0; i < 16; i++) {
                    asm volatile("ld.global.nc.L1::no_allocate.v4.u32 {%0, %1, %2, %3}, [%4];" : "=r"(fa[i][0]), "=r"(fa[i][1]), "=r"(fa[i][2]), "=r"(fa[i][3]) : "l"((const uint4*)c_tab + i * 128 + t));
                }
                if (t == 0) PROFX(91);
                const uint32_t ua = sb + OFF_U + (lane >> 4) * 4096 + (8 * w + (lane & 7)) * 128 + ((((lane >> 3) & 1) ^ (lane & 7)) << 4);
                float acc[4][32];
                const uint64_t db = make_desc(sb + OFF_U, 8192, 1024);
                mbar_wait(bars + 8 * BAR_X, 0);
                if (t == 0) PROF(8);
                uint32_t x[4][8], y[4][8];
#pragma unroll
                for (int m = 0; m < 6; m++) {
                    if (m >= 2) {
                        const int n = m - 2;
                        if (m < 5) wgmma_wait<1>(); else wgmma_wait<0>();
#pragma unroll
                        for (int i = 0; i < 32; i++) asm volatile("" : "+f"(acc[n][i]) :: "memory");
#pragma unroll
                        for (int j = 0; j < 8; j++) { x[n][j] = pack2(acc[n][4 * j], acc[n][4 * j + 1]); y[n][j] = pack2(acc[n][4 * j + 2], acc[n][4 * j + 3]); }
                    }
                    if (m < 4) {
                        wgmma_fence();
                        wgmma_rs_n64<0, 1>(acc[m], fa[4 * m], db + 512 * m);
#pragma unroll
                        for (int j = 1; j < 4; j++) wgmma_rs_n64<1, 1>(acc[m], fa[4 * m + j], db + 512 * m + 128 * j);
                        wgmma_commit();
                    }
                }
                if (t < 4) {
#pragma unroll
                    for (int j = 0; j < 8; j++) {
                        const uint32_t s0 = bf_add2(x[0][j], x[2][j]), s2 = bf_add2(x[1][j], x[3][j]), ty = bf_sub2(y[1][j], y[3][j]), sy = bf_add2(y[1][j], y[3][j]);
                        const uint32_t b0 = y[0][j], b2 = y[2][j];
                        y[1][j] = bf_sub2(x[3][j], x[1][j]); x[1][j] = bf_sub2(x[0][j], x[2][j]);
                        x[0][j] = bf_add2(s0, s2); y[0][j] = bf_sub2(s0, s2);
                        x[2][j] = bf_add2(b0, ty); y[2][j] = bf_add2(sy, b2) ^ 0x80008000u;
                        x[3][j] = bf_sub2(b0, ty); y[3][j] = bf_sub2(b2, sy);
                    }
                } else {
#pragma unroll
                    for (int j = 0; j < 8; j++) {
                        const uint32_t s0x = bf_add2(x[0][j], x[2][j]), s1x = bf_sub2(x[0][j], x[2][j]), s2x = bf_add2(x[1][j], x[3][j]), tx = bf_sub2(x[1][j], x[3][j]);
                        const uint32_t s0y = bf_add2(y[0][j], y[2][j]), s1y = bf_sub2(y[0][j], y[2][j]), s2y = bf_add2(y[1][j], y[3][j]), ty = bf_sub2(y[1][j], y[3][j]);
                        x[0][j] = bf_add2(s0x, s2x); y[0][j] = bf_add2(s0y, s2y);
                        x[1][j] = bf_add2(s1x, ty); y[1][j] = bf_sub2(s1y, tx);
                        x[2][j] = bf_sub2(s0x, s2x); y[2][j] = bf_sub2(s0y, s2y);
                        x[3][j] = bf_sub2(s1x, ty); y[3][j] = bf_add2(s1y, tx);
                    }
                }
                helper_sync();
#pragma unroll
                for (int c = 0; c < 4; c++)
#pragma unroll
                    for (int j = 0; j < 8; j += 2) stsm_x4((ua ^ (j << 4)) + c * 8192, x[c][j], x[c][j + 1], y[c][j], y[c][j + 1]);
                if (t == 0) PROF(21);
            }
            fence_proxy_async_smem();
            __syncwarp();
            if (lane == 0) mbar_arrive(bars + 8 * BAR_S1);
        }
        uint4 tw[8];
        auto load_tw = [&]() {
            const uint4* twp = (const uint4*)kept(2) + lane;
#pragma unroll
            for (int i = 0; i < 8; i++) tw[i] = ldg128(twp + i * 32);
        };
        {
            float acc[2][64];
            float2 lam8[2], lam32[2], lam64[2], wq[2], w4[2], l32q[2], ex[2];
            float2 ag[2][4];
            if (main_cta) {
                int sp = wg * SLOT_OF(16);
                ring_steps<0>(acc, sb, fb, 16, 5 - wg, sp, phm, true, lane == 0, 2 * wg, 2 + wg, 16 * wg);
                mbar_wait(bars + 8 * BAR_S1, 0);
                const uint4* ap = (const uint4*)kept(1) + ((tc - 1 - q) * 512 + (dt + 8 * wg) * 32 + (t >> 2));
                const uint64_t k0 = kept(0);
                const uint32_t fl = (uint32_t)k0, tag = ((uint32_t)(k0 >> 32) & 7) | 8;
                const bool swapB = fl & 128;
                float2 lam1[2], coef[2];
#pragma unroll
                for (int i = 0; i < 2; i++) {
                    const uint4 kv = lds128u(sb + OFF_K + (64 * wg + 32 * i + (t >> 2)) * 16);
                    lam1[i] = make_float2(__uint_as_float(kv.x), __uint_as_float(kv.y));
                    coef[i] = make_float2(__uint_as_float(kv.z), __uint_as_float(kv.w));
                    float2 z = cmul(lam1[i], lam1[i]);
                    z = cmul(z, z);
                    lam8[i] = cmul(z, z);
                    z = cmul(lam8[i], lam8[i]);
                    lam32[i] = cmul(z, z); lam64[i] = cmul(lam32[i], lam32[i]);
                    const float2 l128 = cmul(lam64[i], lam64[i]), l256 = cmul(l128, l128), one = make_float2(1.f, 0.f);
                    w4[i] = cmul(l256, l256);
                    wq[i] = cmul((q & 1) ? l128 : one, (q & 2) ? l256 : one);
                    l32q[i] = cmul((q & 1) ? lam32[i] : one, (q & 2) ? lam64[i] : one);
                    asm volatile("" : "+f"(w4[i].x), "+f"(w4[i].y), "+f"(wq[i].x), "+f"(wq[i].y), "+f"(l32q[i].x), "+f"(l32q[i].y));
                }
                pause(0);
                wgmma_wait_all(acc[0]);
#pragma unroll
                for (int o = 0; o < 64; o++) asm volatile("" : "+f"(acc[1][o]) :: "memory");
                if (lane == 0) mbar_arrive(bars + 8 * (BAR_EMPTY + sp));
                if (tid == 0) PROF(3);
                if (tid == 128) PROF(25);
                if (tid == 224) PROFG(12);
                float2 v[2];
#pragma unroll
                for (int c = 0; c < 8; c++) ag[c >> 2][c & 3] = make_float2(acc[c >> 2][16 * (c & 3)], acc[c >> 2][16 * (c & 3) + 2]);
#pragma unroll
                for (int r = 1; r < 8; r++)
#pragma unroll
                    for (int c = 0; c < 8; c++) {
                        const int i = c >> 2, o = 16 * (c & 3) + 4 * (r >> 1) + (r & 1);
                        ag[i][c & 3] = cfma(lam1[i], ag[i][c & 3], make_float2(acc[i][o], acc[i][o + 2]));
                    }
#pragma unroll
                for (int i = 0; i < 2; i++) {
                    v[i] = ag[i][0];
#pragma unroll
                    for (int c = 1; c < 4; c++) v[i] = cfma(lam8[i], v[i], ag[i][c]);
                    float2 n = make_float2(__shfl_up_sync(0xffffffffu, v[i].x, 1, 4), __shfl_up_sync(0xffffffffu, v[i].y, 1, 4));
                    if (q >= 1) v[i] = cfma(lam32[i], n, v[i]);
                    n = make_float2(__shfl_up_sync(0xffffffffu, v[i].x, 2, 4), __shfl_up_sync(0xffffffffu, v[i].y, 2, 4));
                    if (q >= 2) v[i] = cfma(lam64[i], n, v[i]);
                }
                if (q == 3 && tc < 15) {
                    asm volatile("{\n.reg .b64 a, b;\nmov.b64 a, {%1, %2};\nmov.b64 b, {%3, %4};\nst.relaxed.gpu.global.v2.b64 [%0], {a, b};\n}"
                        :: "l"(ap + 2048), "r"((__float_as_uint(v[0].x) & ~15u) | tag), "r"(__float_as_uint(v[0].y)),
                           "r"((__float_as_uint(v[1].x) & ~15u) | tag), "r"(__float_as_uint(v[1].y)) : "memory");
                }
                PROFS(72 + 8 * wg);
                pause(0);
                {
                    float m00[2], m01[2], m10[2], m11[2];
                    auto scale = [&](int i, float& x, float& y) { const float u = fmaf(m00[i], x, m01[i] * y); y = fmaf(m10[i], x, m11[i] * y); x = u; };
#pragma unroll
                    for (int i = 0; i < 2; i++) {
                        ex[i] = make_float2(__shfl_up_sync(0xffffffffu, v[i].x, 1, 4), __shfl_up_sync(0xffffffffu, v[i].y, 1, 4));
                        if (q == 0) ex[i] = make_float2(0.f, 0.f);
                        const float cx = coef[i].x, cy = coef[i].y;
                        m00[i] = cx; m01[i] = -cy; m10[i] = -cy; m11[i] = -cx;
                        if (swapB) { m00[i] = -cy; m01[i] = cx; m10[i] = -cx; m11[i] = -cy; }
                        scale(i, ex[i].x, ex[i].y);
                        scale(i, l32q[i].x, l32q[i].y);
                        if (!swapB) { lam1[i].y = -lam1[i].y; lam8[i].y = -lam8[i].y; }
#pragma unroll
                        for (int o = 0; o < 64; o += 4) {
                            scale(i, acc[i][o], acc[i][o + 2]); scale(i, acc[i][o + 1], acc[i][o + 3]);
                            if ((o + 4) % SCB == 0) {
#pragma unroll
                                for (int u = o + 4 - SCB; u < o + 4; u++) asm volatile("" : "+f"(acc[i][u]));
                                pause(0);
                            }
                        }
#pragma unroll
                        for (int c = 0; c < 3; c++) scale(i, ag[i][c].x, ag[i][c].y);
                    }
                }
                PROFS(73 + 8 * wg);
                uint4 rr[4];
#pragma unroll
                for (int n = 0; n < 4; n++) rr[n] = make_uint4(tag, 0u, tag, 0u);
                auto poll = [&]() {
#pragma unroll
                    for (int n = 0; n < 4; n++)
                        asm volatile("{\n.reg .b64 a, b;\n.reg .pred p;\nsetp.lt.s32 p, %5, %6;\nmov.b64 a, {%0, %1};\nmov.b64 b, {%2, %3};\n"
                                     "@p ld.relaxed.gpu.global.v2.b64 {a, b}, [%4];\nmov.b64 {%0, %1}, a;\nmov.b64 {%2, %3}, b;\n}"
                            : "+r"(rr[n].x), "+r"(rr[n].y), "+r"(rr[n].z), "+r"(rr[n].w) : "l"(ap - 2048 * n), "r"(4 * n), "r"(tc - q) : "memory");
                };
                poll();
#pragma unroll 1
                for (unsigned n = 0; n < SPIN_LIMIT; n++) {
                    uint32_t bad = 0;
#pragma unroll
                    for (int j = 0; j < 4; j++) bad |= (rr[j].x ^ tag) | (rr[j].z ^ tag);
                    if (!__any_sync(0xffffffffu, bad & 15)) break;
                    if (n < 3) PROFS(74 + 8 * wg + n);
                    poll();
                }
                float2 part[2] = {make_float2(__uint_as_float(rr[3].x), __uint_as_float(rr[3].y)), make_float2(__uint_as_float(rr[3].z), __uint_as_float(rr[3].w))};
#pragma unroll
                for (int n = 2; n >= 0; n--) {
                    part[0] = cfma(w4[0], part[0], make_float2(__uint_as_float(rr[n].x), __uint_as_float(rr[n].y)));
                    part[1] = cfma(w4[1], part[1], make_float2(__uint_as_float(rr[n].z), __uint_as_float(rr[n].w)));
                }
#pragma unroll
                for (int i = 0; i < 2; i++) {
                    part[i] = cmul(wq[i], part[i]);
                    part[i].x += __shfl_xor_sync(0xffffffffu, part[i].x, 1); part[i].y += __shfl_xor_sync(0xffffffffu, part[i].y, 1);
                    part[i].x += __shfl_xor_sync(0xffffffffu, part[i].x, 2); part[i].y += __shfl_xor_sync(0xffffffffu, part[i].y, 2);
                    if (!swapB) part[i].y = -part[i].y;
                    ex[i] = cfma(l32q[i], part[i], ex[i]);
#pragma unroll
                    for (int c = 0; c < 4; c++) { const float2 n = cfma(lam8[i], ex[i], ag[i][c]); ag[i][c] = ex[i]; ex[i] = n; }
                }
                if (t == 0) PROF(4 + 25 * wg);
                const uint32_t hs = sb + OFF_HS + w * 512 + ((lane * 16) ^ ((lane << 1) & 48));
#pragma unroll
                for (int i = 0; i < 2; i++) {
                    if (fl & (4 << i)) {
#pragma unroll
                        for (int r = 0; r < 8; r++)
#pragma unroll
                            for (int c = 0; c < 4; c++) {
                                const int o = 16 * c + 4 * (r >> 1) + (r & 1);
                                ag[i][c] = cfma(lam1[i], ag[i][c], make_float2(acc[i][o], acc[i][o + 2]));
                                acc[i][o] = ag[i][c].x; acc[i][o + 2] = ag[i][c].y;
                            }
                    }
                    if (i) {
                        fence_proxy_async_smem();
                        __syncwarp();
                        if (lane == 0) mbar_arrive(bars + 8 * BAR_HW);
                    }
                    mbar_wait(bars + 8 * (wg ? (i ? BAR_WR : BAR_HD) : BAR_EMPTY + 4), 0);
#pragma unroll
                    for (int z = 0; z < 8; z++) {
                        const float* a = &acc[i][2 * z];
                        sts128u(hs + i * (16384 + wg * 18432) + (z & 1) * 8192 + (z >> 1) * 2048, pack2(a[0], a[16]), pack2(a[32], a[48]), pack2(a[1], a[17]), pack2(a[33], a[49]));
                    }
                }
                fence_proxy_async_smem();
                __syncwarp();
                if (lane == 0) mbar_arrive(bars + 8 * (BAR_HW + 1));
                load_tw();
                if (t == 0) PROF(5 + 25 * wg);
            } else {
                mbar_wait(bars + 8 * BAR_S1, 0);
                load_tw();
            }
        }
        if (wg) mbar_wait(bars + 8 * BAR_WR, 0);
#pragma unroll 1
        for (int ps = wg ? C0 : 0; ps < (wg ? 3 : C0); ps++) {
            if (ps != 1) {
                mbar_wait(bars + (ps ? 8 * BAR_CD : 8 * BAR_U), 0);
                if (t == 0) PROF(ps ? 7 : 23);
                radix8<R8L>(sb, sb + OFF_G + 256 * ps, w, lane, 5 + wg, []() {});
                if (t == 0) PROF(ps ? 24 : 22);
                if (ps) break;
                bar_sync(5, 128);
            }
            mbar_wait(bars + 8 * (BAR_C + ps), 0);
            phase_c(sb, 2 * w + ps, (b == 0 && ps == 0) ? (4 - w) & 3 : 3 - w, lane, tw);
            fence_proxy_async_smem();
            __syncwarp();
            if (lane == 0) {
                mbar_arrive(bars + 8 * BAR_CD);
                if (!wg) mbar_arrive(bars + 8 * BAR_WR);
            }
        }
        const int m0 = 64 * mq + 8 * w;
        if (wg == 0) {
            if (main_cta) {
                float acc[2][64];
                int s = SLOT_OF(32);
#pragma unroll 1
                for (int sg = 0;; sg++) {
                    ring_steps<1>(acc, sb, fb, sg ? 28 - VPOS : VPOS, NS, s, phm, !sg, lane == 0, sg ? 0 : 3, 0, 32 + sg * VPOS);
                    if (sg) break;
                    wgmma_wait<0>();
                    if (lane == 0) mbar_arrive(bars + 8 * (BAR_EMPTY + s));
                    __syncwarp();
                    s = SLOT_OF(36 + VPOS);
                }
#pragma unroll
                for (int i = 0; i < 2; i++) {
#pragma unroll
                    for (int k = 0; k < 4; k++) {
                        const int s = SLOT_OF(64 + k);
                        if (i == 0) { mbar_wait(fb + 8 * s, (phm >> s) & 1); PROFK(60 + k); }
                        const uint64_t da = make_desc(sb + s * SLOT + i * 8192, 4096, 512, 2), db = make_desc(sb + s * SLOT + 16384, 16, 1024);
                        wgmma_fence();
#pragma unroll
                        for (int j = 0; j < 4; j++) wgmma_n128<1, 0>(acc[i], da + 64 * j, db + 2 * j, 1);
                        if (i == 0 && k == 0) {
                            wgmma_commit();
                            wgmma_wait<1>();
                            if (lane == 0) mbar_arrive(bars + 8 * (BAR_EMPTY + SLOT_OF(63)));
                            __syncwarp();
                        }
                    }
                    wgmma_commit();
                }
                bar_sync(4, 256);
                const CUtensorMap* maps = (const CUtensorMap*)kept(3);
                float sc[2][2];
#pragma unroll
                for (int i = 0; i < 4; i++) sc[i >> 1][i & 1] = lds32f(sb + OFF_SC + (8 * w + 32 * (i >> 1) + 4 * (i & 1) + (g & 3)) * 8 + (g >> 2) * 4);
                const uint32_t rw = 2 * (g & 3) + (g >> 2);
                const uint32_t ob = sb + OFF_HS + w * 2048, oa = ob + rw * 128 + (((q >> 1) ^ rw) << 4) + (q & 1) * 8;
                const uint32_t ea = sb + OFF_U + (16 * w + (lane & 15)) * 128 + (((lane >> 4) ^ (lane & 7) ^ ((lane >> 1) & 4)) << 4);
#pragma unroll
                for (int i = 0; i < 2; i++) {
                    uint32_t e[8][4];
#pragma unroll
                    for (int j = 0; j < 8; j++) ldsm_x4(e[j], (ea ^ ((j & 3) << 5)) + (j >> 2) * 16384 + i * 8192);
                    if (i) wgmma_wait<0>(); else wgmma_wait<1>();
#pragma unroll
                    for (int o = 0; o < 64; o++) asm volatile("" : "+f"(acc[i][o]) :: "memory");
                    if (tid == 0) PROF(17 + i);
                    if (tid == 96 && i) PROFG(20);
#pragma unroll
                    for (int c = 0; c < 4; c++) {
#pragma unroll
                        for (int j = 0; j < 8; j++) {
                            const int o = 16 * c + 2 * j;
                            const uint32_t ev = e[2 * c + (j >> 2)][j & 3];
                            sts64((oa ^ ((j >> 1) << 5)) + c * 8192 + i * 32768 + (j & 1) * 1024,
                                  fmaf(sc[i][j & 1], acc[i][o], bf_lo(ev)), fmaf(sc[i][j & 1], acc[i][o + 1], bf_hi(ev)));
                        }
                        fence_proxy_async_smem();
                        __syncwarp();
                        if (elect()) tma_store_4d(maps + 9, ob + c * 8192 + i * 32768, 128 * dt + 32 * c, 0, rp, m0 + 32 * i);
                    }
                }
                if (elect()) {
                    bulk_commit();
                    bulk_wait_read();
                }
                if (tid == 0) PROF(19);
                if (tid == 96) { PROF(20); PROFG(4); }
            }
        } else {
            fence_proxy_async_smem();
            __syncwarp();
            if (lane == 0) mbar_arrive(bars + 8 * BAR_VW);
            __syncwarp();
            if (tid == 224) PROFG(16);
            if (main_cta) {
                {
                    if (T_G) pause(T_G);
                    uint4 gw[4], xv[16];
#pragma unroll
                    for (int i = 0; i < 4; i++) gw[i] = ldg128((const uint4*)P.gate_w + lane + 32 * i);
#pragma unroll
                    for (int i = 0; i < 16; i++) xv[i] = ldg128((const uint4*)P.x + (16 * b + 4 * w) * 128 + lane + 32 * i);
                    float gs[4] = {0.f, 0.f, 0.f, 0.f};
#pragma unroll
                    for (int i = 0; i < 16; i++) {
                        const uint32_t p0 = bf_mul2(xv[i].x, gw[i & 3].x), p1 = bf_mul2(xv[i].y, gw[i & 3].y), p2 = bf_mul2(xv[i].z, gw[i & 3].z), p3 = bf_mul2(xv[i].w, gw[i & 3].w);
                        gs[i >> 2] += ((bf_lo(p0) + bf_hi(p0)) + (bf_lo(p1) + bf_hi(p1))) + ((bf_lo(p2) + bf_hi(p2)) + (bf_lo(p3) + bf_hi(p3)));
                    }
#pragma unroll
                    for (int i = 0; i < 2; i++) gs[i] = ((lane & 16) ? gs[i + 2] : gs[i]) + __shfl_xor_sync(0xffffffffu, (lane & 16) ? gs[i] : gs[i + 2], 16);
                    float u = ((lane & 8) ? gs[1] : gs[0]) + __shfl_xor_sync(0xffffffffu, (lane & 8) ? gs[0] : gs[1], 8);
#pragma unroll
                    for (int o = 1; o < 8; o <<= 1) u += __shfl_xor_sync(0xffffffffu, u, o);
                    const float gg = bf_round(__fdividef(1.f, 1.f + __expf(-bf_round(u))));
                    if ((lane & 7) == 0) sts64(sb + OFF_GS + t, gg, bf_round(1.f - gg));
                    fence_proxy_async_smem();
                    __syncwarp();
                    if (lane == 0) mbar_arrive(bars + 8 * (BAR_HW + 2));
                }
                float acc[2][64];
                uint32_t dk[16];
#pragma unroll
                for (int j = 0; j < 16; j++) dk[j] = ldg32u(P.dskip + 128 * dt + 8 * j + 2 * q);
                mbar_wait(bars + 8 * BAR_T, 1);
#pragma unroll
                for (int k = 0; k < 4; k++) {
                    const int s = SLOT_OF(32 + VPOS + k);
                    mbar_wait(fb + 8 * s, (phm >> s) & 1);
                    PROFK(64 + k);
                    const uint64_t da = make_desc(sb + OFF_T + k * 8192, 4096, 512, 2), db = make_desc(sb + s * SLOT, 8192, 1024);
                    wgmma_fence();
#pragma unroll
                    for (int j = 0; j < 4; j++) {
                        wgmma_n128<1, 1>(acc[0], da + 64 * j, db + 128 * j, (k | j) != 0);
                        wgmma_n128<1, 1>(acc[1], da + 64 * j, db + 1024 + 128 * j, (k | j) != 0);
                    }
                    wgmma_commit();
                    if (k) {
                        wgmma_wait<1>();
                        if (lane == 0) mbar_arrive(bars + 8 * (BAR_EMPTY + SLOT_OF(31 + VPOS + k)));
                        __syncwarp();
                    }
                }
                wgmma_wait_all(acc[0]);
#pragma unroll
                for (int o = 0; o < 64; o++) asm volatile("" : "+f"(acc[1][o]) :: "memory");
                if (lane == 0) mbar_arrive(bars + 8 * (BAR_EMPTY + SLOT_OF(35 + VPOS)));
                if (t == 0) PROF(15);
                float4 gt[2];
                mbar_wait(bars + 8 * BAR_U, 1);
#pragma unroll
                for (int i = 0; i < 2; i++) gt[i] = __ldcg((const float4*)&g_gate[8 * (m0 + 8 * w + 8 * i + g) + 2 * rp]);
                uint32_t ev[2][32];
#pragma unroll
                for (int o = 0; o < 64; o++) ev[o >> 5][o & 31] = pack2(acc[o >> 5][2 * (o & 31)], acc[o >> 5][2 * (o & 31) + 1]);
                mbar_wait(bars + 8 * BAR_X, 1);
                const uint32_t xa = sb + OFF_U + (16 * w + (lane & 15)) * 128 + (((lane >> 4) ^ (lane & 7)) << 4);
                auto dup = [](float v) { return __byte_perm(__float_as_uint(v), 0, 0x3232); };
#pragma unroll
                for (int e = 0; e < 2; e++) {
                    const uint32_t g0 = dup(e ? gt[0].z : gt[0].x), g1 = dup(e ? gt[1].z : gt[1].x), o0 = dup(e ? gt[0].w : gt[0].y), o1 = dup(e ? gt[1].w : gt[1].y);
#pragma unroll
                    for (int j = 0; j < 8; j++) {
                        uint32_t x[4];
                        ldsm_x4(x, (xa ^ ((j & 3) << 5)) + e * 8192 + (j >> 2) * 16384);
#pragma unroll
                        for (int c = 0; c < 4; c++)
                            ev[e][4 * j + c] = bf_fma2(ev[e][4 * j + c], (c & 1) ? g1 : g0, bf_mul2(bf_mul2(x[c], dk[2 * j + (c >> 1)]), (c & 1) ? o1 : o0));
                    }
                }
#pragma unroll
                for (int i = 0; i < 2; i++) if (q == 0) sts64(sb + OFF_SC + (16 * w + 8 * i + g) * 8, 2.f * gt[i].y, 2.f * gt[i].w);
                bar_sync(6, 128);
                const uint32_t ea = sb + OFF_U + (32 * w + 2 * (lane & 12) + (lane & 3)) * 128 + (((lane >> 4) ^ (lane & 7)) << 4);
#pragma unroll
                for (int e = 0; e < 2; e++)
#pragma unroll
                    for (int j = 0; j < 8; j++)
                        stsm_x4((ea ^ ((j & 3) << 5) ^ (e << 6)) + e * 512 + (j >> 2) * 16384, ev[e][4 * j], ev[e][4 * j + 1], ev[e][4 * j + 2], ev[e][4 * j + 3]);
                bar_arrive(4, 256);
                if (t == 0) PROF(16);
            }
            if (t == 0) {
                const unsigned old = atomicAdd(&g_cnt[CNT_DONE * CS], 1u);
                if (old == 128) { g_cnt[CNT_DONE * CS] = 0; g_cnt[CNT_EPOCH * CS] = (uint32_t)(kept(0) >> 32); }
            }
        }
    } else {
        reg_dealloc<REG_H>();
        const int w = warp - 8;
        if (w == 0) {
            if (elect()) {
                PROF(0);
#pragma unroll
                for (int i = 0; i < 5; i++) mbar_init(bars + 8 * i, 1);
                mbar_init(bars + 8 * BAR_X, 1);
                fence_barrier_init();
                fence_proxy_async_smem();
                PROFX(88);
            }
            __syncwarp();
            bar_arrive(0, 384);
            if (elect()) {
                if (main_cta) {
#pragma unroll 1
                    for (int k = 0; k < 5; k++) {
                        load_g1(k, k);
                        if (k == 0) PROFX(89);
                        if (P_R0) pause(P_R0);
                    }
                }
                PROF(27);
            }
            __syncwarp();
            bar_sync(7, 64);
            if (main_cta && elect()) {
                int s = 0; uint32_t ph = 0;
#pragma unroll 1
                for (int k = 5; k < 68; k++) {
                    mbar_wait(bars + 8 * (BAR_EMPTY + s), ph);
                    if (k < 32) {
                        load_g1(k, s);
                    } else {
                        const uint32_t st = sb + s * SLOT;
                        const unsigned kv = k - 32 - VPOS;
                        if (kv < 4) {
                            const uint32_t full = bars + 8 * (BAR_FULL + 5 + s);
                            if (kv == 0) mbar_wait(bars + 8 * (BAR_F + 2), 0);
                            mbar_expect_tx(full, SLOT);
                            tma_load_3d(st, &mapV, full, 0, kv * 64, rp * 32 + dt * 2);
                            tma_load_3d(st + 16384, &mapV, full, 0, kv * 64, rp * 32 + 16 + dt * 2);
                        } else {
                            const uint32_t full = bars + 8 * (BAR_FULL + s);
                            const int h = k < 32 + VPOS ? k - 32 : k - 36;
                            mbar_expect_tx(full, SLOT);
                            tma_load_3d(st + 16384, &mapCre + (h & 1), full, 0, dt * 128, h >> 1);
                            if ((h & 15) == 0) mbar_wait(bars + 8 * (BAR_F + (h >> 4)), 0);
                            bulk_load(st, g_hT + (h * 16 + tc) * 16384, 16384, full);
                        }
                    }
                    if (++s == (k < 15 ? 5 : NS)) { s = 0; ph ^= 1; }
                }
            }
        } else {
            const unsigned epoch = load_epoch();
            bar_sync(0, 384);
            if (w == 1) {
                bar_arrive(7, 64);
                if (elect()) {
                    if (main_cta) {
                        mbar_expect_tx(bars + 8 * BAR_X, 32768);
                        pause(T_XS + D_XS * (b & 15));
#pragma unroll 1
                        for (int c = 0; c < 4; c++) {
                            tma_load_4d(sb + OFF_U + c * 8192, &mapXs, bars + 8 * BAR_X, (b & 15) * 64, 0, c, b >> 4);
                            pause(P_XS);
                        }
                    }
                    mbar_wait(bars + 8 * BAR_S1, 0);
                    if (main_cta) {
#pragma unroll
                        for (int c = 0; c < 4; c++) {
                            if (c) pause(PACE_U);
                            tma_store_4d(&mapU0, sb + OFF_U + c * 8192, (b & 15) * 64, 32 * c, 0, b >> 4);
                        }
                        bulk_commit();
                        bulk_wait0();
                        signal_counter(&g_cnt[CNT_U * CS]);
                    }
                    PROF(9);
                    mbar_expect_tx(bars + 8 * BAR_U, 32768);
                    wait_counter(&g_cnt[CNT_U * CS], epoch * 128);
                    PROF(11);
#pragma unroll
                    for (int i = 0; i < 8; i++) {
                        if (PACE_L && i && !(i & 1)) pause(PACE_L);
                        tma_load_4d(sb + OFF_U + i * 4096, &mapU2, bars + 8 * BAR_U, 0, 0, (i & 3) * 4, b == 128 ? 1 : b == 0 ? 0 : 2 * b + (i >> 2));
                    }
                    if (main_cta) {
#pragma unroll 1
                        for (int i = 0; i < 2; i++) {
                            mbar_wait(bars + 8 * BAR_HW, i);
                            tma_store_3d(&mapH, sb + OFF_HS, 0, 2 * tc, (dt + 8 * i) * 8);
                            mbar_wait(bars + 8 * (BAR_HW + 1), i);
                            tma_store_3d(&mapH, sb + OFF_W + i * 18432, 0, 2 * tc + 1, (dt + 8 * i) * 8);
                            bulk_commit();
                            bulk_wait0();
                            signal_counter(&g_cnt[(CNT_H + i) * CS]);
                            mbar_arrive(bars + 8 * (BAR_HD + i));
                            PROF(i ? 6 : 26);
                            wait_counter(&g_cnt[(CNT_H + i) * CS], epoch * 128);
                            mbar_arrive(bars + 8 * (BAR_F + i));
                            PROF(1 + i);
                        }
                    }
                }
            } else {
                const int ld = (1026 * cls) >> 7, lm = (1026 * ((256 - cls) & 255)) >> 7;
                if (elect() && main_cta) {
                    if (w == 3) {
                        pause(T_W);
#pragma unroll 1
                        for (int i = 0; i < 8; i++) {
                            tma_prefetch_4d(&mapWr + (i & 1), 0, (i & 2) ? lm : ld, i >> 2, 0);
                            pause(200);
                        }
                        bulk_prefetch_l2(c_inv + b * 128, 1024);
                    } else {
                        pause(T_BA + D_XS * tc);
                        if (tc > 4) tma_prefetch_4d(&mapB, tc * 64, 0, 0, dt * 8);
                        pause(T_B2);
                        bulk_prefetch_l2(((b & 1) ? P.b_im : P.b_re) + (64 + (b >> 1)) * 8192, 16384);
                        pause(T_W0 - D_XS * tc);
                    }
                }
#pragma unroll 1
                for (int ps = 0; ps < 2; ps++) {
                    const uint32_t wb = sb + OFF_W + (1 - ps) * 18432;
                    if (w == 2 && elect()) {
                        const uint32_t bw = bars + 8 * (BAR_W + ps);
                        if (ps && main_cta) mbar_wait(bars + 8 * BAR_HD, 0);
                        mbar_expect_tx(bw, ps ? 18432 : 18432 + 8192);
#pragma unroll 1
                        for (int i = 0; i < 4; i++) {
                            tma_load_4d(wb + (i >> 1) * 4608 + (i & 1) * 9216, &mapWr + (i & 1), bw, 0, i < 2 ? ld : lm, (i < 2 || b == 0) ? ps : 1 - ps, 0);
                            pause(P_W);
                        }
                        if (!ps) bulk_load(sb + OFF_F, c_tab + 8192, 8192, bw);
                        PROFX(85 + ps);
                    }
                    __syncwarp();
                    mbar_wait(bars + 8 * (BAR_W + ps), 0);
                    if (tid == 320) PROF(ps ? 31 : 10);
#pragma unroll 1
                    for (int u = 0; u < 4; u++) {
                        const int row = 2 * (w - 2) + (u >> 1), pl = u & 1;
                        const uint32_t dp = wb + pl * 9216 + row * 1152, mp = wb + pl * 9216 + 4608 + ((b == 0 && ps == 0) ? (4 - row) & 3 : 3 - row) * 1152;
                        const uint32_t od = dp + ((1026 * cls) & 127), om = mp + ((1026 * (256 - cls)) & 127);
                        uint32_t v[4][8], o[4][4];
#pragma unroll
                        for (int i = 0; i < 8; i++) {
                            const uint4 r = lds128u((i < 4 ? (od & ~15u) + 16 * lane + (i >> 1) * 512 : ((om + 1010) & ~15u) - 16 * lane - ((i >> 1) & 1) * 512) + (i & 1) * 16);
                            uint32_t* d = &v[i >> 1][4 * (i & 1)];
                            d[0] = r.x; d[1] = r.y; d[2] = r.z; d[3] = r.w;
                        }
                        const uint32_t e0 = lds16(om), e1 = lds16(od + 1024);
                        auto fwd = [&](int ws) {
#pragma unroll
                            for (int k = 0; k < 8; k++) o[k >> 2][k & 3] = __byte_perm(v[k >> 2][ws + (k & 3)], v[k >> 2][ws + (k & 3) + 1], (cls & 1) ? 0x5432 : 0x3210);
                        };
                        auto mir = [&](int ws) {
#pragma unroll
                            for (int k = 8; k < 16; k++) o[k >> 2][k & 3] = __byte_perm(v[k >> 2][ws + 3 - (k & 3)], v[k >> 2][ws + 4 - (k & 3)], (cls & 1) ? 0x1032 : 0x3254);
                        };
                        switch ((cls >> 1) & 3) { case 0: fwd(0); break; case 1: fwd(1); break; case 2: fwd(2); break; default: fwd(3); }
                        switch (((1 - cls) >> 1) & 3) { case 0: mir(0); break; case 1: mir(1); break; case 2: mir(2); break; default: mir(3); }
                        if (lane == 0) {
                            o[0][0] = pack2(fmaf(pl ? -0.5f : 0.5f, bf_lo(e0), 0.5f * bf_lo(o[0][0])), bf_hi(o[0][0]));
                            o[2][0] = pack2(fmaf(pl ? -0.5f : 0.5f, bf_lo(e1), 0.5f * bf_lo(o[2][0])), bf_hi(o[2][0]));
                        }
                        __syncwarp();
#pragma unroll
                        for (int i = 0; i < 4; i++)
                            sts128u((i < 2 ? dp : mp) + (i & 1) * 512 + ((lane * 16) ^ ((lane << 1) & 48)), o[i][0], o[i][1], o[i][2], o[i][3]);
                    }
                    if (ps) fence_proxy_async_smem();
                    mbar_arrive(bars + 8 * (BAR_C + ps));
                    if (tid == 320) PROF(ps ? 12 : 28);
                }
                if (main_cta) {
                    if (elect()) {
#pragma unroll 1
                        for (int i = 0; i < 4; i++) {
                            bulk_prefetch_l2(((b & 1) ? P.c_im : P.c_re) + (size_t)(b >> 1) * 16384 + (w - 2) * 8192 + i * 2048, 4096);
                            pause(500);
                        }
                    }
                }
                if (elect()) {
                    if (w == 3) {
                        if (main_cta) {
                            mbar_wait(bars + 8 * BAR_CD, 0);
                            mbar_wait(bars + 8 * (BAR_HD + 1), 0);
                            mbar_expect_tx(bars + 8 * BAR_T, 32768);
#pragma unroll 1
                            for (int j = 0; j < 4; j++) {
                                bulk_load(sb + OFF_T + j * 8192, c_inv + mq * 4096 + j * 1024, 8192, bars + 8 * BAR_T);
                                pause(300);
                            }
                            mbar_wait(bars + 8 * (BAR_HW + 2), 0);
                            bulk_store(g_gate + 16 * b, sb + OFF_GS, 128);
                            bulk_commit();
                            bulk_wait0();
                            signal_counter(&g_cnt[CNT_G * CS]);
                            wait_counter(&g_cnt[CNT_G * CS], epoch * 128);
                            mbar_arrive(bars + 8 * BAR_U);
                            PROFX(95);
                        }
                    } else {
                        mbar_wait(bars + 8 * BAR_VW, 0);
#pragma unroll 1
                        for (int i = 0; i < (real_cls ? 4 : 8); i++) {
                            if (i) pause(PACE_V);
                            tma_store_4d(&mapU2, sb + OFF_U + i * 4096, 0, 0, (i & 3) * 4, b == 128 ? 1 : 2 * b + (i >> 2));
                        }
                        bulk_commit();
                        bulk_wait0();
                        signal_counter(&g_cnt[CNT_V * CS]);
                        PROF(13);
                        if (main_cta) {
                            wait_counter(&g_cnt[CNT_V * CS], epoch * 129);
                            mbar_arrive(bars + 8 * (BAR_F + 2));
                            PROF(14);
                            mbar_expect_tx(bars + 8 * BAR_X, 32768);
#pragma unroll 1
                            for (int i = 0; i < 4; i++) {
                                pause(P_XE);
                                tma_load_3d(sb + OFF_U + i * 8192, &mapXe, bars + 8 * BAR_X, 128 * dt + 64 * (i >> 1), 64 * mq, 2 * rp + (i & 1));
                            }
                        }
                    }
                }
            }
        }
    }
}

typedef CUresult (*PFN_encodeTiled)(CUtensorMap*, CUtensorMapDataType, cuuint32_t, void*, const cuuint64_t*, const cuuint64_t*,
                                    const cuuint32_t*, const cuuint32_t*, CUtensorMapInterleave, CUtensorMapSwizzle,
                                    CUtensorMapL2promotion, CUtensorMapFloatOOBfill);

static CUtensorMap make_map(PFN_encodeTiled enc, const void* ptr, int rank, const cuuint64_t* dims, const cuuint64_t* strides, const cuuint32_t* box,
                            CUtensorMapSwizzle sw = CU_TENSOR_MAP_SWIZZLE_128B, CUtensorMapDataType dt = CU_TENSOR_MAP_DATA_TYPE_BFLOAT16) {
    CUtensorMap m;
    cuuint32_t es[5] = {1, 1, 1, 1, 1};
    enc(&m, dt, rank, (void*)ptr, dims, strides, box, es, CU_TENSOR_MAP_INTERLEAVE_NONE,
        sw, CU_TENSOR_MAP_L2_PROMOTION_L2_128B, CU_TENSOR_MAP_FLOAT_OOB_FILL_NONE);
    return m;
}

extern "C" void kernel_launch(void* const* d_in, const int* in_sizes, int n_in, void* d_out, int out_size) {
    const bf16* x = (const bf16*)d_in[0];
    const bf16* wr = (const bf16*)d_in[1];
    const bf16* wi = (const bf16*)d_in[2];
    const bf16* Bre = (const bf16*)d_in[6];
    const bf16* Bim = (const bf16*)d_in[7];
    const bf16* Cre = (const bf16*)d_in[8];
    const bf16* Cim = (const bf16*)d_in[9];

    void* fn = nullptr;
    cudaDriverEntryPointQueryResult st;
    cudaGetDriverEntryPoint("cuTensorMapEncodeTiled", &fn, cudaEnableDefault, &st);
    PFN_encodeTiled enc = (PFN_encodeTiled)fn;
    void *p_hT, *p_U;
    cudaGetSymbolAddress(&p_hT, g_hT);
    cudaGetSymbolAddress(&p_U, g_U);

    Params P;
    P.lam_re = (const bf16*)d_in[4]; P.lam_im = (const bf16*)d_in[5]; P.log_dt = (const bf16*)d_in[10];
    P.dskip = (const bf16*)d_in[11]; P.gate_w = (const bf16*)d_in[12]; P.c_re = Cre; P.c_im = Cim; P.b_re = Bre; P.b_im = Bim; P.x = x;
    P.swapB = Bim < Bre;

    CUtensorMap mB, mX, mCre, mCim, mXs, mU0, mV, mU2, mXe, mO, mWr, mWi, mH;
    {
        cuuint64_t d[4] = {64, 2052, 2, 4}, s[3] = {128, 262656, 525312};
        cuuint32_t bx[4] = {64, 9, 1, 4};
        mWr = make_map(enc, wr, 4, d, s, bx, CU_TENSOR_MAP_SWIZZLE_NONE);
        mWi = make_map(enc, wi, 4, d, s, bx, CU_TENSOR_MAP_SWIZZLE_NONE);
    }
    {
        cuuint64_t d[3] = {256, 32, 128}, s[2] = {2048, 65536};
        cuuint32_t bx[3] = {256, 1, 8};
        mH = make_map(enc, p_hT, 3, d, s, bx, CU_TENSOR_MAP_SWIZZLE_NONE, CU_TENSOR_MAP_DATA_TYPE_UINT64);
    }
    {
        const bf16* lo = P.swapB ? Bim : Bre; const bf16* hi = P.swapB ? Bre : Bim;
        cuuint64_t d[4] = {1024, 8, 2, 128}, s[3] = {2048, (cuuint64_t)((const char*)hi - (const char*)lo), 16384};
        cuuint32_t bx[4] = {64, 8, 2, 8};
        mB = make_map(enc, lo, 4, d, s, bx);
    }
    {
        cuuint64_t d[4] = {1024, 2, 4, 976}, s[3] = {2048, 32 * 2048, 2 * 2048};
        cuuint32_t bx[4] = {64, 2, 4, 16};
        mX = make_map(enc, x, 4, d, s, bx);
    }
    {
        cuuint64_t d[3] = {64, 1024, 16}, s[2] = {2048, 128};
        cuuint32_t bx[3] = {64, 128, 1};
        mCre = make_map(enc, Cre, 3, d, s, bx);
        mCim = make_map(enc, Cim, 3, d, s, bx);
    }
    {
        cuuint64_t d[3] = {64, 256, 128}, s[2] = {16384, 128};
        cuuint32_t bx[3] = {64, 64, 2};
        mV = make_map(enc, p_U, 3, d, s, bx);
    }
    {
        cuuint64_t d[3] = {1024, 256, 8}, s[2] = {8 * 2048, 2048};
        cuuint32_t bx[3] = {64, 64, 1};
        mXe = make_map(enc, x, 3, d, s, bx);
    }
    {
        cuuint64_t d[4] = {1024, 2, 4, 256}, s[3] = {4096, 2 * 4096, 8 * 4096};
        cuuint32_t bx[4] = {32, 2, 1, 8};
        mO = make_map(enc, d_out, 4, d, s, bx, CU_TENSOR_MAP_SWIZZLE_128B, CU_TENSOR_MAP_DATA_TYPE_FLOAT32);
    }
    {
        cuuint64_t d[4] = {1024, 64, 4, 8}, s[3] = {32 * 2048, 8 * 2048, 2048};
        cuuint32_t bx[4] = {64, 64, 1, 1};
        mXs = make_map(enc, x, 4, d, s, bx);
    }
    {
        cuuint64_t d[4] = {1024, 128, 2, 8}, s[3] = {32768, 16384, 2048};
        cuuint32_t bx[4] = {64, 32, 2, 1};
        mU0 = make_map(enc, p_U, 4, d, s, bx);
    }
    {
        cuuint64_t d[4] = {64, 8, 16, 256}, s[3] = {2048, 128, 16384};
        cuuint32_t bx[4] = {64, 8, 4, 1};
        mU2 = make_map(enc, p_U, 4, d, s, bx);
    }
    cudaFuncSetAttribute(fused_kernel, cudaFuncAttributeMaxDynamicSharedMemorySize, SMEM_BYTES);
    fused_kernel<<<130, 384, SMEM_BYTES, cudaStreamPerThread>>>(mB, mX, mXs, mU0, mU2, mXe, mCre, mCim, mV, mO, mWr, mWi, mH, P);
}
```

```cpp
#include <cuda_runtime.h>
#include <cuda_bf16.h>
#include <cuda.h>
#include <stdint.h>

typedef __nv_bfloat16 bf16;

__device__ const __align__(128) uint32_t c_tab[11264] = {
0x3f803f80,0xbf803f80,0x3f803f80,0xbf803f80,0x3f803f80,0xbf803f80,0x3f803f80,0xbf803f80,0x3f803f80,0xbf803f80,0x3f803f80,0xbf803f80,
0x3f803f80,0xbf803f80,0x3f803f80,0xbf803f80,0x3f7f3f80,0xbdc98000,0x3f223f35,0xbf46bf35,0x3f753f7b,0xbe95be48,0x3ef13f0e,0xbf62bf55,
0x3f623f6d,0xbef1bec4,0x3e953ec4,0xbf75bf6d,0x3f463f55,0xbf22bf0e,0x3dc93e48,0xbf7fbf7b,0x3f7b3f80,0xbe488000,0xbe480000,0xbf7bbf80,
0x3f553f6d,0xbf0ebec4,0xbf0ebec4,0xbf55bf6d,0x3f0e3f35,0xbf55bf35,0xbf55bf35,0xbf0ebf35,0x3e483ec4,0xbf7bbf6d,0xbf7bbf6d,0xbe48bec4,
0x3f753f80,0xbe958000,0xbf62bf35,0xbef1bf35,0x3f223f55,0xbf46bf0e,0xbf7fbf7b,0x3dc9be48,0x3dc93ec4,0xbf7fbf6d,0xbf46bf6d,0x3f223ec4,
0xbef1be48,0xbf62bf7b,0xbe95bf0e,0x3f753f55,0x3f6d3f80,0xbec48000,0xbf6dbf80,0x3ec48000,0x3ec43f35,0xbf6dbf35,0xbec4bf35,0x3f6d3f35,
0xbec40000,0xbf6dbf80,0x3ec40000,0x3f6d3f80,0xbf6dbf35,0xbec4bf35,0x3f6d3f35,0x3ec43f35,0x3f623f80,0xbef18000,0xbe95bf35,0x3f753f35,
0x3dc93f0e,0xbf7fbf55,0x3f223e48,0x3f463f7b,0xbf46bec4,0xbf22bf6d,0x3f7f3f6d,0xbdc93ec4,0xbf75bf7b,0x3e95be48,0x3ef13f55,0xbf62bf0e,
0x3f553f80,0xbf0e8000,0x3f0e0000,0x3f553f80,0xbe483ec4,0xbf7bbf6d,0x3f7b3f6d,0xbe483ec4,0xbf7bbf35,0xbe48bf35,0x3e483f35,0xbf7bbf35,
0xbf0ebf6d,0x3f553ec4,0xbf55bec4,0xbf0ebf6d,0x3f463f80,0xbf228000,0x3f7f3f35,0x3dc93f35,0xbef13e48,0xbf62bf7b,0x3e953f55,0xbf75bf0e,
0xbf75bf6d,0x3e95bec4,0xbf62bec4,0xbef1bf6d,0x3dc9bf0e,0x3f7f3f55,0xbf22bf7b,0x3f463e48,0x3f353f80,0xbf358000,0x3f353f80,0xbf358000,
0xbf350000,0xbf35bf80,0xbf350000,0xbf35bf80,0xbf35bf80,0x3f358000,0xbf35bf80,0x3f358000,0x3f350000,0x3f353f80,0x3f350000,0x3f353f80,
0x3f223f80,0xbf468000,0xbdc93f35,0xbf7fbf35,0xbf62be48,0xbef1bf7b,0xbf75bf55,0x3e95bf0e,0xbe95bf6d,0x3f753ec4,0x3ef1bec4,0x3f623f6d,
0x3f7f3f0e,0x3dc93f55,0x3f463f7b,0xbf223e48,0x3f0e3f80,0xbf558000,0xbf550000,0xbf0ebf80,0xbf7bbec4,0xbe48bf6d,0xbe48bf6d,0x3f7b3ec4,
0x3e48bf35,0x3f7b3f35,0x3f7b3f35,0xbe483f35,0x3f553f6d,0xbf0e3ec4,0xbf0e3ec4,0xbf55bf6d,0x3ef13f80,0xbf628000,0xbf75bf35,0x3e95bf35,
0xbf7fbf0e,0x3dc9bf55,0x3f46be48,0x3f223f7b,0x3f22bec4,0x3f463f6d,0x3dc93f6d,0xbf7fbec4,0x3e953f7b,0xbf75be48,0xbf62bf55,0x3ef1bf0e,
0x3ec43f80,0xbf6d8000,0xbec4bf80,0x3f6d8000,0xbf6dbf35,0x3ec4bf35,0x3f6d3f35,0xbec43f35,0x3f6d0000,0x3ec43f80,0xbf6d0000,0xbec4bf80,
0xbec43f35,0xbf6dbf35,0x3ec4bf35,0x3f6d3f35,0x3e953f80,0xbf758000,0x3ef1bf35,0x3f623f35,0xbf46bf55,0x3f22bf0e,0x3dc93f7b,0xbf7fbe48,
0x3f7f3ec4,0xbdc93f6d,0xbf22bf6d,0x3f46bec4,0xbf623e48,0xbef1bf7b,0x3f753f0e,0xbe953f55,0x3e483f80,0xbf7b8000,0x3f7b0000,0x3e483f80,
0xbf0ebf6d,0x3f55bec4,0xbf553ec4,0xbf0ebf6d,0x3f553f35,0xbf0e3f35,0x3f0ebf35,0x3f553f35,0xbf7bbec4,0x3e48bf6d,0xbe483f6d,0xbf7bbec4,
0x3dc93f80,0xbf7f8000,0x3f463f35,0xbf223f35,0xbe95bf7b,0x3f75be48,0xbf62bf0e,0x3ef1bf55,0x3ef13f6d,0xbf623ec4,0x3f753ec4,0xbe953f6d,
0xbf22bf55,0x3f46bf0e,0xbf7fbe48,0x3dc9bf7b,0x3f80,0xbf808000,0x3f80,0xbf808000,0xbf80,0x3f808000,0xbf80,0x3f808000,
0x3f80,0xbf808000,0x3f80,0xbf808000,0xbf80,0x3f808000,0xbf80,0x3f808000,0xbdc93f80,0xbf7f8000,0xbf463f35,0xbf22bf35,
0x3e95bf7b,0x3f753e48,0x3f62bf0e,0x3ef13f55,0xbef13f6d,0xbf62bec4,0xbf753ec4,0xbe95bf6d,0x3f22bf55,0x3f463f0e,0x3f7fbe48,0x3dc93f7b,
0xbe483f80,0xbf7b8000,0xbf7b0000,0x3e48bf80,0x3f0ebf6d,0x3f553ec4,0x3f553ec4,0xbf0e3f6d,0xbf553f35,0xbf0ebf35,0xbf0ebf35,0x3f55bf35,
0x3f7bbec4,0x3e483f6d,0x3e483f6d,0xbf7b3ec4,0xbe953f80,0xbf758000,0xbef1bf35,0x3f62bf35,0x3f46bf55,0x3f223f0e,0xbdc93f7b,0xbf7f3e48,
0xbf7f3ec4,0xbdc9bf6d,0x3f22bf6d,0x3f463ec4,0x3f623e48,0xbef13f7b,0xbf753f0e,0xbe95bf55,0xbec43f80,0xbf6d8000,0x3ec4bf80,0x3f6d8000,
0x3f6dbf35,0x3ec43f35,0xbf6d3f35,0xbec4bf35,0xbf6d0000,0x3ec4bf80,0x3f6d0000,0xbec43f80,0x3ec43f35,0xbf6d3f35,0xbec4bf35,0x3f6dbf35,
0xbef13f80,0xbf628000,0x3f75bf35,0x3e953f35,0x3f7fbf0e,0x3dc93f55,0xbf46be48,0x3f22bf7b,0xbf22bec4,0x3f46bf6d,0xbdc93f6d,0xbf7f3ec4,
0xbe953f7b,0xbf753e48,0x3f62bf55,0x3ef13f0e,0xbf0e3f80,0xbf558000,0x3f550000,0xbf0e3f80,0x3f7bbec4,0xbe483f6d,0x3e48bf6d,0x3f7bbec4,
0xbe48bf35,0x3f7bbf35,0xbf7b3f35,0xbe48bf35,0xbf553f6d,0xbf0ebec4,0x3f0e3ec4,0xbf553f6d,0xbf223f80,0xbf468000,0x3dc93f35,0xbf7f3f35,
0x3f62be48,0xbef13f7b,0x3f75bf55,0x3e953f0e,0x3e95bf6d,0x3f75bec4,0xbef1bec4,0x3f62bf6d,0xbf7f3f0e,0x3dc9bf55,0xbf463f7b,0xbf22be48,
0xbf353f80,0xbf358000,0xbf353f80,0xbf358000,0x3f350000,0xbf353f80,0x3f350000,0xbf353f80,0x3f35bf80,0x3f358000,0x3f35bf80,0x3f358000,
0xbf350000,0x3f35bf80,0xbf350000,0x3f35bf80,0xbf463f80,0xbf228000,0xbf7f3f35,0x3dc9bf35,0x3ef13e48,0xbf623f7b,0xbe953f55,0xbf753f0e,
0x3f75bf6d,0x3e953ec4,0x3f62bec4,0xbef13f6d,0xbdc9bf0e,0x3f7fbf55,0x3f22bf7b,0x3f46be48,0xbf553f80,0xbf0e8000,0xbf0e0000,0x3f55bf80,
0x3e483ec4,0xbf7b3f6d,0xbf7b3f6d,0xbe48bec4,0x3f7bbf35,0xbe483f35,0xbe483f35,0xbf7b3f35,0x3f0ebf6d,0x3f55bec4,0x3f55bec4,0xbf0e3f6d,
0xbf623f80,0xbef18000,0x3e95bf35,0x3f75bf35,0xbdc93f0e,0xbf7f3f55,0xbf223e48,0x3f46bf7b,0x3f46bec4,0xbf223f6d,0xbf7f3f6d,0xbdc9bec4,
0x3f75bf7b,0x3e953e48,0xbef13f55,0xbf623f0e,0xbf6d3f80,0xbec48000,0x3f6dbf80,0x3ec48000,0xbec43f35,0xbf6d3f35,0x3ec4bf35,0x3f6dbf35,
0x3ec40000,0xbf6d3f80,0xbec40000,0x3f6dbf80,0x3f6dbf35,0xbec43f35,0xbf6d3f35,0x3ec4bf35,0xbf753f80,0xbe958000,0x3f62bf35,0xbef13f35,
0xbf223f55,0xbf463f0e,0x3f7fbf7b,0x3dc93e48,0xbdc93ec4,0xbf7f3f6d,0x3f46bf6d,0x3f22bec4,0x3ef1be48,0xbf623f7b,0x3e95bf0e,0x3f75bf55,
0xbf7b3f80,0xbe488000,0x3e480000,0xbf7b3f80,0xbf553f6d,0xbf0e3ec4,0x3f0ebec4,0xbf553f6d,0xbf0e3f35,0xbf553f35,0x3f55bf35,0xbf0e3f35,
0xbe483ec4,0xbf7b3f6d,0x3f7bbf6d,0xbe483ec4,0xbf7f3f80,0xbdc98000,0xbf223f35,0xbf463f35,0xbf753f7b,0xbe953e48,0xbef13f0e,0xbf623f55,
0xbf623f6d,0xbef13ec4,0xbe953ec4,0xbf753f6d,0xbf463f55,0xbf223f0e,0xbdc93e48,0xbf7f3f7b,0x3f803f80,0xbf803f80,0x3f803f80,0xbf803f80,
0x3f803f80,0xbf803f80,0x3f803f80,0xbf803f80,0x3f803f80,0xbf803f80,0x3f803f80,0xbf803f80,0x3f803f80,0xbf803f80,0x3f803f80,0xbf803f80,
0xbdc90000,0xbf7fbf80,0xbf46bf35,0xbf22bf35,0xbe95be48,0xbf75bf7b,0xbf62bf55,0xbef1bf0e,0xbef1bec4,0xbf62bf6d,0xbf75bf6d,0xbe95bec4,
0xbf22bf0e,0xbf46bf55,0xbf7fbf7b,0xbdc9be48,0xbf7bbf80,0x3e488000,0x3e480000,0x3f7b3f80,0xbf55bf6d,0x3f0e3ec4,0x3f0e3ec4,0x3f553f6d,
0xbf0ebf35,0x3f553f35,0x3f553f35,0x3f0e3f35,0xbe48bec4,0x3f7b3f6d,0x3f7b3f6d,0x3e483ec4,0x3e950000,0x3f753f80,0x3ef13f35,0xbf62bf35,
0x3f463f0e,0x3f223f55,0xbdc93e48,0xbf7fbf7b,0x3f7f3f6d,0x3dc93ec4,0xbf22bec4,0xbf46bf6d,0x3f623f7b,0xbef1be48,0xbf75bf55,0xbe95bf0e,
0x3f6d3f80,0xbec48000,0xbf6dbf80,0x3ec48000,0x3ec43f35,0xbf6dbf35,0xbec4bf35,0x3f6d3f35,0xbec40000,0xbf6dbf80,0x3ec40000,0x3f6d3f80,
0xbf6dbf35,0xbec4bf35,0x3f6d3f35,0x3ec43f35,0xbef10000,0xbf62bf80,0x3f753f35,0x3e953f35,0xbf7fbf55,0xbdc9bf0e,0x3f463f7b,0xbf22be48,
0xbf22bf6d,0x3f463ec4,0xbdc93ec4,0xbf7fbf6d,0x3e95be48,0x3f753f7b,0xbf62bf0e,0xbef1bf55,0xbf55bf80,0x3f0e8000,0xbf0e0000,0xbf55bf80,
0x3e48bec4,0x3f7b3f6d,0xbf7bbf6d,0x3e48bec4,0x3f7b3f35,0x3e483f35,0xbe48bf35,0x3f7b3f35,0x3f0e3f6d,0xbf55bec4,0x3f553ec4,0x3f0e3f6d,
0x3f220000,0x3f463f80,0xbdc9bf35,0x3f7f3f35,0x3f623f7b,0xbef13e48,0x3f753f0e,0x3e953f55,0xbe953ec4,0xbf75bf6d,0x3ef13f6d,0xbf62bec4,
0xbf7fbf55,0x3dc9bf0e,0xbf46be48,0xbf22bf7b,0x3f353f80,0xbf358000,0x3f353f80,0xbf358000,0xbf350000,0xbf35bf80,0xbf350000,0xbf35bf80,
0xbf35bf80,0x3f358000,0xbf35bf80,0x3f358000,0x3f350000,0x3f353f80,0x3f350000,0x3f353f80,0xbf460000,0xbf22bf80,0xbf7fbf35,0x3dc9bf35,
0xbef1bf7b,0x3f623e48,0x3e95bf0e,0x3f753f55,0x3f753ec4,0x3e953f6d,0x3f623f6d,0xbef13ec4,0x3dc93f55,0xbf7fbf0e,0xbf223e48,0xbf46bf7b,
0xbf0ebf80,0x3f558000,0x3f550000,0x3f0e3f80,0x3f7b3ec4,0x3e483f6d,0x3e483f6d,0xbf7bbec4,0xbe483f35,0xbf7bbf35,0xbf7bbf35,0x3e48bf35,
0xbf55bf6d,0x3f0ebec4,0x3f0ebec4,0x3f553f6d,0x3f620000,0x3ef13f80,0xbe953f35,0xbf75bf35,0xbdc93f55,0xbf7fbf0e,0xbf22bf7b,0x3f46be48,
0xbf46bf6d,0x3f22bec4,0x3f7f3ec4,0x3dc93f6d,0x3f753e48,0x3e953f7b,0xbef13f0e,0xbf62bf55,0x3ec43f80,0xbf6d8000,0xbec4bf80,0x3f6d8000,
0xbf6dbf35,0x3ec4bf35,0x3f6d3f35,0xbec43f35,0x3f6d0000,0x3ec43f80,0xbf6d0000,0xbec4bf80,0xbec43f35,0xbf6dbf35,0x3ec4bf35,0x3f6d3f35,
0xbf750000,0xbe95bf80,0x3f623f35,0xbef13f35,0x3f22bf0e,0x3f463f55,0xbf7fbe48,0xbdc9bf7b,0xbdc93f6d,0xbf7fbec4,0x3f46bec4,0x3f223f6d,
0xbef1bf7b,0x3f62be48,0xbe953f55,0xbf75bf0e,0xbe48bf80,0x3f7b8000,0xbf7b0000,0xbe48bf80,0x3f0e3f6d,0xbf553ec4,0x3f55bec4,0x3f0e3f6d,
0xbf55bf35,0x3f0ebf35,0xbf0e3f35,0xbf55bf35,0x3f7b3ec4,0xbe483f6d,0x3e48bf6d,0x3f7b3ec4,0x3f7f0000,0x3dc93f80,0x3f22bf35,0x3f463f35,
0xbf753e48,0xbe95bf7b,0xbef13f55,0xbf62bf0e,0x3f62bec4,0x3ef13f6d,0x3e95bf6d,0x3f753ec4,0xbf463f0e,0xbf22bf55,0xbdc93f7b,0xbf7fbe48,
0x3f80,0xbf808000,0x3f80,0xbf808000,0xbf80,0x3f808000,0xbf80,0x3f808000,0x3f80,0xbf808000,0x3f80,0xbf808000,
0xbf80,0x3f808000,0xbf80,0x3f808000,0xbf7f0000,0x3dc9bf80,0xbf22bf35,0x3f46bf35,0x3f753e48,0xbe953f7b,0x3ef13f55,0xbf623f0e,
0xbf62bec4,0x3ef1bf6d,0xbe95bf6d,0x3f75bec4,0x3f463f0e,0xbf223f55,0x3dc93f7b,0xbf7f3e48,0x3e48bf80,0x3f7b8000,0x3f7b0000,0xbe483f80,
0xbf0e3f6d,0xbf55bec4,0xbf55bec4,0x3f0ebf6d,0x3f55bf35,0x3f0e3f35,0x3f0e3f35,0xbf553f35,0xbf7b3ec4,0xbe48bf6d,0xbe48bf6d,0x3f7bbec4,
0x3f750000,0xbe953f80,0xbf623f35,0xbef1bf35,0xbf22bf0e,0x3f46bf55,0x3f7fbe48,0xbdc93f7b,0x3dc93f6d,0xbf7f3ec4,0xbf46bec4,0x3f22bf6d,
0x3ef1bf7b,0x3f623e48,0x3e953f55,0xbf753f0e,0xbec43f80,0xbf6d8000,0x3ec4bf80,0x3f6d8000,0x3f6dbf35,0x3ec43f35,0xbf6d3f35,0xbec4bf35,
0xbf6d0000,0x3ec4bf80,0x3f6d0000,0xbec43f80,0x3ec43f35,0xbf6d3f35,0xbec4bf35,0x3f6dbf35,0xbf620000,0x3ef1bf80,0x3e953f35,0xbf753f35,
0x3dc93f55,0xbf7f3f0e,0x3f22bf7b,0x3f463e48,0x3f46bf6d,0x3f223ec4,0xbf7f3ec4,0x3dc9bf6d,0xbf753e48,0x3e95bf7b,0x3ef13f0e,0xbf623f55,
0x3f0ebf80,0x3f558000,0xbf550000,0x3f0ebf80,0xbf7b3ec4,0x3e48bf6d,0xbe483f6d,0xbf7b3ec4,0x3e483f35,0xbf7b3f35,0x3f7bbf35,0x3e483f35,
0x3f55bf6d,0x3f0e3ec4,0xbf0ebec4,0x3f55bf6d,0x3f460000,0xbf223f80,0x3f7fbf35,0x3dc93f35,0x3ef1bf7b,0x3f62be48,0xbe95bf0e,0x3f75bf55,
0xbf753ec4,0x3e95bf6d,0xbf623f6d,0xbef1bec4,0xbdc93f55,0xbf7f3f0e,0x3f223e48,0xbf463f7b,0xbf353f80,0xbf358000,0xbf353f80,0xbf358000,
0x3f350000,0xbf353f80,0x3f350000,0xbf353f80,0x3f35bf80,0x3f358000,0x3f35bf80,0x3f358000,0xbf350000,0x3f35bf80,0xbf350000,0x3f35bf80,
0xbf220000,0x3f46bf80,0x3dc9bf35,0x3f7fbf35,0xbf623f7b,0xbef1be48,0xbf753f0e,0x3e95bf55,0x3e953ec4,0xbf753f6d,0xbef13f6d,0xbf623ec4,
0x3f7fbf55,0x3dc93f0e,0x3f46be48,0xbf223f7b,0x3f55bf80,0x3f0e8000,0x3f0e0000,0xbf553f80,0xbe48bec4,0x3f7bbf6d,0x3f7bbf6d,0x3e483ec4,
0xbf7b3f35,0x3e48bf35,0x3e48bf35,0x3f7bbf35,0xbf0e3f6d,0xbf553ec4,0xbf553ec4,0x3f0ebf6d,0x3ef10000,0xbf623f80,0xbf753f35,0x3e95bf35,
0x3f7fbf55,0xbdc93f0e,0xbf463f7b,0xbf223e48,0x3f22bf6d,0x3f46bec4,0x3dc93ec4,0xbf7f3f6d,0xbe95be48,0x3f75bf7b,0x3f62bf0e,0xbef13f55,
0xbf6d3f80,0xbec48000,0x3f6dbf80,0x3ec48000,0xbec43f35,0xbf6d3f35,0x3ec4bf35,0x3f6dbf35,0x3ec40000,0xbf6d3f80,0xbec40000,0x3f6dbf80,
0x3f6dbf35,0xbec43f35,0xbf6d3f35,0x3ec4bf35,0xbe950000,0x3f75bf80,0xbef13f35,0xbf623f35,0xbf463f0e,0x3f22bf55,0x3dc93e48,0xbf7f3f7b,
0xbf7f3f6d,0x3dc9bec4,0x3f22bec4,0xbf463f6d,0xbf623f7b,0xbef13e48,0x3f75bf55,0xbe953f0e,0x3f7bbf80,0x3e488000,0xbe480000,0x3f7bbf80,
0x3f55bf6d,0x3f0ebec4,0xbf0e3ec4,0x3f55bf6d,0x3f0ebf35,0x3f55bf35,0xbf553f35,0x3f0ebf35,0x3e48bec4,0x3f7bbf6d,0xbf7b3f6d,0x3e48bec4,
0x3dc90000,0xbf7f3f80,0x3f46bf35,0xbf223f35,0x3e95be48,0xbf753f7b,0x3f62bf55,0xbef13f0e,0x3ef1bec4,0xbf623f6d,0x3f75bf6d,0xbe953ec4,
0x3f22bf0e,0xbf463f55,0x3f7fbf7b,0xbdc93e48,0x3f803f80,0xbf803f80,0x3f803f80,0xbf803f80,0x3f803f80,0xbf803f80,0x3f803f80,0xbf803f80,
0x3f803f80,0xbf803f80,0x3f803f80,0xbf803f80,0x3f803f80,0xbf803f80,0x3f803f80,0xbf803f80,0xbf7fbf80,0x3dc98000,0xbf22bf35,0x3f463f35,
0xbf75bf7b,0x3e953e48,0xbef1bf0e,0x3f623f55,0xbf62bf6d,0x3ef13ec4,0xbe95bec4,0x3f753f6d,0xbf46bf55,0x3f223f0e,0xbdc9be48,0x3f7f3f7b,
0x3f7b3f80,0xbe488000,0xbe480000,0xbf7bbf80,0x3f553f6d,0xbf0ebec4,0xbf0ebec4,0xbf55bf6d,0x3f0e3f35,0xbf55bf35,0xbf55bf35,0xbf0ebf35,
0x3e483ec4,0xbf7bbf6d,0xbf7bbf6d,0xbe48bec4,0xbf75bf80,0x3e958000,0x3f623f35,0x3ef13f35,0xbf22bf55,0x3f463f0e,0x3f7f3f7b,0xbdc93e48,
0xbdc9bec4,0x3f7f3f6d,0x3f463f6d,0xbf22bec4,0x3ef13e48,0x3f623f7b,0x3e953f0e,0xbf75bf55,0x3f6d3f80,0xbec48000,0xbf6dbf80,0x3ec48000,
0x3ec43f35,0xbf6dbf35,0xbec4bf35,0x3f6d3f35,0xbec40000,0xbf6dbf80,0x3ec40000,0x3f6d3f80,0xbf6dbf35,0xbec4bf35,0x3f6d3f35,0x3ec43f35,
0xbf62bf80,0x3ef18000,0x3e953f35,0xbf75bf35,0xbdc9bf0e,0x3f7f3f55,0xbf22be48,0xbf46bf7b,0x3f463ec4,0x3f223f6d,0xbf7fbf6d,0x3dc9bec4,
0x3f753f7b,0xbe953e48,0xbef1bf55,0x3f623f0e,0x3f553f80,0xbf0e8000,0x3f0e0000,0x3f553f80,0xbe483ec4,0xbf7bbf6d,0x3f7b3f6d,0xbe483ec4,
0xbf7bbf35,0xbe48bf35,0x3e483f35,0xbf7bbf35,0xbf0ebf6d,0x3f553ec4,0xbf55bec4,0xbf0ebf6d,0xbf46bf80,0x3f228000,0xbf7fbf35,0xbdc9bf35,
0x3ef1be48,0x3f623f7b,0xbe95bf55,0x3f753f0e,0x3f753f6d,0xbe953ec4,0x3f623ec4,0x3ef13f6d,0xbdc93f0e,0xbf7fbf55,0x3f223f7b,0xbf46be48,
0x3f353f80,0xbf358000,0x3f353f80,0xbf358000,0xbf350000,0xbf35bf80,0xbf350000,0xbf35bf80,0xbf35bf80,0x3f358000,0xbf35bf80,0x3f358000,
0x3f350000,0x3f353f80,0x3f350000,0x3f353f80,0xbf22bf80,0x3f468000,0x3dc9bf35,0x3f7f3f35,0x3f623e48,0x3ef13f7b,0x3f753f55,0xbe953f0e,
0x3e953f6d,0xbf75bec4,0xbef13ec4,0xbf62bf6d,0xbf7fbf0e,0xbdc9bf55,0xbf46bf7b,0x3f22be48,0x3f0e3f80,0xbf558000,0xbf550000,0xbf0ebf80,
0xbf7bbec4,0xbe48bf6d,0xbe48bf6d,0x3f7b3ec4,0x3e48bf35,0x3f7b3f35,0x3f7b3f35,0xbe483f35,0x3f553f6d,0xbf0e3ec4,0xbf0e3ec4,0xbf55bf6d,
0xbef1bf80,0x3f628000,0x3f753f35,0xbe953f35,0x3f7f3f0e,0xbdc93f55,0xbf463e48,0xbf22bf7b,0xbf223ec4,0xbf46bf6d,0xbdc9bf6d,0x3f7f3ec4,
0xbe95bf7b,0x3f753e48,0x3f623f55,0xbef13f0e,0x3ec43f80,0xbf6d8000,0xbec4bf80,0x3f6d8000,0xbf6dbf35,0x3ec4bf35,0x3f6d3f35,0xbec43f35,
0x3f6d0000,0x3ec43f80,0xbf6d0000,0xbec4bf80,0xbec43f35,0xbf6dbf35,0x3ec4bf35,0x3f6d3f35,0xbe95bf80,0x3f758000,0xbef13f35,0xbf62bf35,
0x3f463f55,0xbf223f0e,0xbdc9bf7b,0x3f7f3e48,0xbf7fbec4,0x3dc9bf6d,0x3f223f6d,0xbf463ec4,0x3f62be48,0x3ef13f7b,0xbf75bf0e,0x3e95bf55,
0x3e483f80,0xbf7b8000,0x3f7b0000,0x3e483f80,0xbf0ebf6d,0x3f55bec4,0xbf553ec4,0xbf0ebf6d,0x3f553f35,0xbf0e3f35,0x3f0ebf35,0x3f553f35,
0xbf7bbec4,0x3e48bf6d,0xbe483f6d,0xbf7bbec4,0xbdc9bf80,0x3f7f8000,0xbf46bf35,0x3f22bf35,0x3e953f7b,0xbf753e48,0x3f623f0e,0xbef13f55,
0xbef1bf6d,0x3f62bec4,0xbf75bec4,0x3e95bf6d,0x3f223f55,0xbf463f0e,0x3f7f3e48,0xbdc93f7b,0x3f80,0xbf808000,0x3f80,0xbf808000,
0xbf80,0x3f808000,0xbf80,0x3f808000,0x3f80,0xbf808000,0x3f80,0xbf808000,0xbf80,0x3f808000,0xbf80,0x3f808000,
0x3dc9bf80,0x3f7f8000,0x3f46bf35,0x3f223f35,0xbe953f7b,0xbf75be48,0xbf623f0e,0xbef1bf55,0x3ef1bf6d,0x3f623ec4,0x3f75bec4,0x3e953f6d,
0xbf223f55,0xbf46bf0e,0xbf7f3e48,0xbdc9bf7b,0xbe483f80,0xbf7b8000,0xbf7b0000,0x3e48bf80,0x3f0ebf6d,0x3f553ec4,0x3f553ec4,0xbf0e3f6d,
0xbf553f35,0xbf0ebf35,0xbf0ebf35,0x3f55bf35,0x3f7bbec4,0x3e483f6d,0x3e483f6d,0xbf7b3ec4,0x3e95bf80,0x3f758000,0x3ef13f35,0xbf623f35,
0xbf463f55,0xbf22bf0e,0x3dc9bf7b,0x3f7fbe48,0x3f7fbec4,0x3dc93f6d,0xbf223f6d,0xbf46bec4,0xbf62be48,0x3ef1bf7b,0x3f75bf0e,0x3e953f55,
0xbec43f80,0xbf6d8000,0x3ec4bf80,0x3f6d8000,0x3f6dbf35,0x3ec43f35,0xbf6d3f35,0xbec4bf35,0xbf6d0000,0x3ec4bf80,0x3f6d0000,0xbec43f80,
0x3ec43f35,0xbf6d3f35,0xbec4bf35,0x3f6dbf35,0x3ef1bf80,0x3f628000,0xbf753f35,0xbe95bf35,0xbf7f3f0e,0xbdc9bf55,0x3f463e48,0xbf223f7b,
0x3f223ec4,0xbf463f6d,0x3dc9bf6d,0x3f7fbec4,0x3e95bf7b,0x3f75be48,0xbf623f55,0xbef1bf0e,0xbf0e3f80,0xbf558000,0x3f550000,0xbf0e3f80,
0x3f7bbec4,0xbe483f6d,0x3e48bf6d,0x3f7bbec4,0xbe48bf35,0x3f7bbf35,0xbf7b3f35,0xbe48bf35,0xbf553f6d,0xbf0ebec4,0x3f0e3ec4,0xbf553f6d,
0x3f22bf80,0x3f468000,0xbdc9bf35,0x3f7fbf35,0xbf623e48,0x3ef1bf7b,0xbf753f55,0xbe95bf0e,0xbe953f6d,0xbf753ec4,0x3ef13ec4,0xbf623f6d,
0x3f7fbf0e,0xbdc93f55,0x3f46bf7b,0x3f223e48,0xbf353f80,0xbf358000,0xbf353f80,0xbf358000,0x3f350000,0xbf353f80,0x3f350000,0xbf353f80,
0x3f35bf80,0x3f358000,0x3f35bf80,0x3f358000,0xbf350000,0x3f35bf80,0xbf350000,0x3f35bf80,0x3f46bf80,0x3f228000,0x3f7fbf35,0xbdc93f35,
0xbef1be48,0x3f62bf7b,0x3e95bf55,0x3f75bf0e,0xbf753f6d,0xbe95bec4,0xbf623ec4,0x3ef1bf6d,0x3dc93f0e,0xbf7f3f55,0xbf223f7b,0xbf463e48,
0xbf553f80,0xbf0e8000,0xbf0e0000,0x3f55bf80,0x3e483ec4,0xbf7b3f6d,0xbf7b3f6d,0xbe48bec4,0x3f7bbf35,0xbe483f35,0xbe483f35,0xbf7b3f35,
0x3f0ebf6d,0x3f55bec4,0x3f55bec4,0xbf0e3f6d,0x3f62bf80,0x3ef18000,0xbe953f35,0xbf753f35,0x3dc9bf0e,0x3f7fbf55,0x3f22be48,0xbf463f7b,
0xbf463ec4,0x3f22bf6d,0x3f7fbf6d,0x3dc93ec4,0xbf753f7b,0xbe95be48,0x3ef1bf55,0x3f62bf0e,0xbf6d3f80,0xbec48000,0x3f6dbf80,0x3ec48000,
0xbec43f35,0xbf6d3f35,0x3ec4bf35,0x3f6dbf35,0x3ec40000,0xbf6d3f80,0xbec40000,0x3f6dbf80,0x3f6dbf35,0xbec43f35,0xbf6d3f35,0x3ec4bf35,
0x3f75bf80,0x3e958000,0xbf623f35,0x3ef1bf35,0x3f22bf55,0x3f46bf0e,0xbf7f3f7b,0xbdc9be48,0x3dc9bec4,0x3f7fbf6d,0xbf463f6d,0xbf223ec4,
0xbef13e48,0x3f62bf7b,0xbe953f0e,0xbf753f55,0xbf7b3f80,0xbe488000,0x3e480000,0xbf7b3f80,0xbf553f6d,0xbf0e3ec4,0x3f0ebec4,0xbf553f6d,
0xbf0e3f35,0xbf553f35,0x3f55bf35,0xbf0e3f35,0xbe483ec4,0xbf7b3f6d,0x3f7bbf6d,0xbe483ec4,0x3f7fbf80,0x3dc98000,0x3f22bf35,0x3f46bf35,
0x3f75bf7b,0x3e95be48,0x3ef1bf0e,0x3f62bf55,0x3f62bf6d,0x3ef1bec4,0x3e95bec4,0x3f75bf6d,0x3f46bf55,0x3f22bf0e,0x3dc9be48,0x3f7fbf7b,
0x3f803f80,0xbf803f80,0x3f803f80,0xbf803f80,0x3f803f80,0xbf803f80,0x3f803f80,0xbf803f80,0x3f803f80,0xbf803f80,0x3f803f80,0xbf803f80,
0x3f803f80,0xbf803f80,0x3f803f80,0xbf803f80,0x3dc90000,0x3f7f3f80,0x3f463f35,0x3f223f35,0x3e953e48,0x3f753f7b,0x3f623f55,0x3ef13f0e,
0x3ef13ec4,0x3f623f6d,0x3f753f6d,0x3e953ec4,0x3f223f0e,0x3f463f55,0x3f7f3f7b,0x3dc93e48,0xbf7bbf80,0x3e488000,0x3e480000,0x3f7b3f80,
0xbf55bf6d,0x3f0e3ec4,0x3f0e3ec4,0x3f553f6d,0xbf0ebf35,0x3f553f35,0x3f553f35,0x3f0e3f35,0xbe48bec4,0x3f7b3f6d,0x3f7b3f6d,0x3e483ec4,
0xbe950000,0xbf75bf80,0xbef1bf35,0x3f623f35,0xbf46bf0e,0xbf22bf55,0x3dc9be48,0x3f7f3f7b,0xbf7fbf6d,0xbdc9bec4,0x3f223ec4,0x3f463f6d,
0xbf62bf7b,0x3ef13e48,0x3f753f55,0x3e953f0e,0x3f6d3f80,0xbec48000,0xbf6dbf80,0x3ec48000,0x3ec43f35,0xbf6dbf35,0xbec4bf35,0x3f6d3f35,
0xbec40000,0xbf6dbf80,0x3ec40000,0x3f6d3f80,0xbf6dbf35,0xbec4bf35,0x3f6d3f35,0x3ec43f35,0x3ef10000,0x3f623f80,0xbf75bf35,0xbe95bf35,
0x3f7f3f55,0x3dc93f0e,0xbf46bf7b,0x3f223e48,0x3f223f6d,0xbf46bec4,0x3dc9bec4,0x3f7f3f6d,0xbe953e48,0xbf75bf7b,0x3f623f0e,0x3ef13f55,
0xbf55bf80,0x3f0e8000,0xbf0e0000,0xbf55bf80,0x3e48bec4,0x3f7b3f6d,0xbf7bbf6d,0x3e48bec4,0x3f7b3f35,0x3e483f35,0xbe48bf35,0x3f7b3f35,
0x3f0e3f6d,0xbf55bec4,0x3f553ec4,0x3f0e3f6d,0xbf220000,0xbf46bf80,0x3dc93f35,0xbf7fbf35,0xbf62bf7b,0x3ef1be48,0xbf75bf0e,0xbe95bf55,
0x3e95bec4,0x3f753f6d,0xbef1bf6d,0x3f623ec4,0x3f7f3f55,0xbdc93f0e,0x3f463e48,0x3f223f7b,0x3f353f80,0xbf358000,0x3f353f80,0xbf358000,
0xbf350000,0xbf35bf80,0xbf350000,0xbf35bf80,0xbf35bf80,0x3f358000,0xbf35bf80,0x3f358000,0x3f350000,0x3f353f80,0x3f350000,0x3f353f80,
0x3f460000,0x3f223f80,0x3f7f3f35,0xbdc93f35,0x3ef13f7b,0xbf62be48,0xbe953f0e,0xbf75bf55,0xbf75bec4,0xbe95bf6d,0xbf62bf6d,0x3ef1bec4,
0xbdc9bf55,0x3f7f3f0e,0x3f22be48,0x3f463f7b,0xbf0ebf80,0x3f558000,0x3f550000,0x3f0e3f80,0x3f7b3ec4,0x3e483f6d,0x3e483f6d,0xbf7bbec4,
0xbe483f35,0xbf7bbf35,0xbf7bbf35,0x3e48bf35,0xbf55bf6d,0x3f0ebec4,0x3f0ebec4,0x3f553f6d,0xbf620000,0xbef1bf80,0x3e95bf35,0x3f753f35,
0x3dc9bf55,0x3f7f3f0e,0x3f223f7b,0xbf463e48,0x3f463f6d,0xbf223ec4,0xbf7fbec4,0xbdc9bf6d,0xbf75be48,0xbe95bf7b,0x3ef1bf0e,0x3f623f55,
0x3ec43f80,0xbf6d8000,0xbec4bf80,0x3f6d8000,0xbf6dbf35,0x3ec4bf35,0x3f6d3f35,0xbec43f35,0x3f6d0000,0x3ec43f80,0xbf6d0000,0xbec4bf80,
0xbec43f35,0xbf6dbf35,0x3ec4bf35,0x3f6d3f35,0x3f750000,0x3e953f80,0xbf62bf35,0x3ef1bf35,0xbf223f0e,0xbf46bf55,0x3f7f3e48,0x3dc93f7b,
0x3dc9bf6d,0x3f7f3ec4,0xbf463ec4,0xbf22bf6d,0x3ef13f7b,0xbf623e48,0x3e95bf55,0x3f753f0e,0xbe48bf80,0x3f7b8000,0xbf7b0000,0xbe48bf80,
0x3f0e3f6d,0xbf553ec4,0x3f55bec4,0x3f0e3f6d,0xbf55bf35,0x3f0ebf35,0xbf0e3f35,0xbf55bf35,0x3f7b3ec4,0xbe483f6d,0x3e48bf6d,0x3f7b3ec4,
0xbf7f0000,0xbdc9bf80,0xbf223f35,0xbf46bf35,0x3f75be48,0x3e953f7b,0x3ef1bf55,0x3f623f0e,0xbf623ec4,0xbef1bf6d,0xbe953f6d,0xbf75bec4,
0x3f46bf0e,0x3f223f55,0x3dc9bf7b,0x3f7f3e48,0x3f80,0xbf808000,0x3f80,0xbf808000,0xbf80,0x3f808000,0xbf80,0x3f808000,
0x3f80,0xbf808000,0x3f80,0xbf808000,0xbf80,0x3f808000,0xbf80,0x3f808000,0x3f7f0000,0xbdc93f80,0x3f223f35,0xbf463f35,
0xbf75be48,0x3e95bf7b,0xbef1bf55,0x3f62bf0e,0x3f623ec4,0xbef13f6d,0x3e953f6d,0xbf753ec4,0xbf46bf0e,0x3f22bf55,0xbdc9bf7b,0x3f7fbe48,
0x3e48bf80,0x3f7b8000,0x3f7b0000,0xbe483f80,0xbf0e3f6d,0xbf55bec4,0xbf55bec4,0x3f0ebf6d,0x3f55bf35,0x3f0e3f35,0x3f0e3f35,0xbf553f35,
0xbf7b3ec4,0xbe48bf6d,0xbe48bf6d,0x3f7bbec4,0xbf750000,0x3e95bf80,0x3f62bf35,0x3ef13f35,0x3f223f0e,0xbf463f55,0xbf7f3e48,0x3dc9bf7b,
0xbdc9bf6d,0x3f7fbec4,0x3f463ec4,0xbf223f6d,0xbef13f7b,0xbf62be48,0xbe95bf55,0x3f75bf0e,0xbec43f80,0xbf6d8000,0x3ec4bf80,0x3f6d8000,
0x3f6dbf35,0x3ec43f35,0xbf6d3f35,0xbec4bf35,0xbf6d0000,0x3ec4bf80,0x3f6d0000,0xbec43f80,0x3ec43f35,0xbf6d3f35,0xbec4bf35,0x3f6dbf35,
0x3f620000,0xbef13f80,0xbe95bf35,0x3f75bf35,0xbdc9bf55,0x3f7fbf0e,0xbf223f7b,0xbf46be48,0xbf463f6d,0xbf22bec4,0x3f7fbec4,0xbdc93f6d,
0x3f75be48,0xbe953f7b,0xbef1bf0e,0x3f62bf55,0x3f0ebf80,0x3f558000,0xbf550000,0x3f0ebf80,0xbf7b3ec4,0x3e48bf6d,0xbe483f6d,0xbf7b3ec4,
0x3e483f35,0xbf7b3f35,0x3f7bbf35,0x3e483f35,0x3f55bf6d,0x3f0e3ec4,0xbf0ebec4,0x3f55bf6d,0xbf460000,0x3f22bf80,0xbf7f3f35,0xbdc9bf35,
0xbef13f7b,0xbf623e48,0x3e953f0e,0xbf753f55,0x3f75bec4,0xbe953f6d,0x3f62bf6d,0x3ef13ec4,0x3dc9bf55,0x3f7fbf0e,0xbf22be48,0x3f46bf7b,
0xbf353f80,0xbf358000,0xbf353f80,0xbf358000,0x3f350000,0xbf353f80,0x3f350000,0xbf353f80,0x3f35bf80,0x3f358000,0x3f35bf80,0x3f358000,
0xbf350000,0x3f35bf80,0xbf350000,0x3f35bf80,0x3f220000,0xbf463f80,0xbdc93f35,0xbf7f3f35,0x3f62bf7b,0x3ef13e48,0x3f75bf0e,0xbe953f55,
0xbe95bec4,0x3f75bf6d,0x3ef1bf6d,0x3f62bec4,0xbf7f3f55,0xbdc9bf0e,0xbf463e48,0x3f22bf7b,0x3f55bf80,0x3f0e8000,0x3f0e0000,0xbf553f80,
0xbe48bec4,0x3f7bbf6d,0x3f7bbf6d,0x3e483ec4,0xbf7b3f35,0x3e48bf35,0x3e48bf35,0x3f7bbf35,0xbf0e3f6d,0xbf553ec4,0xbf553ec4,0x3f0ebf6d,
0xbef10000,0x3f62bf80,0x3f75bf35,0xbe953f35,0xbf7f3f55,0x3dc9bf0e,0x3f46bf7b,0x3f22be48,0xbf223f6d,0xbf463ec4,0xbdc9bec4,0x3f7fbf6d,
0x3e953e48,0xbf753f7b,0xbf623f0e,0x3ef1bf55,0xbf6d3f80,0xbec48000,0x3f6dbf80,0x3ec48000,0xbec43f35,0xbf6d3f35,0x3ec4bf35,0x3f6dbf35,
0x3ec40000,0xbf6d3f80,0xbec40000,0x3f6dbf80,0x3f6dbf35,0xbec43f35,0xbf6d3f35,0x3ec4bf35,0x3e950000,0xbf753f80,0x3ef1bf35,0x3f62bf35,
0x3f46bf0e,0xbf223f55,0xbdc9be48,0x3f7fbf7b,0x3f7fbf6d,0xbdc93ec4,0xbf223ec4,0x3f46bf6d,0x3f62bf7b,0x3ef1be48,0xbf753f55,0x3e95bf0e,
0x3f7bbf80,0x3e488000,0xbe480000,0x3f7bbf80,0x3f55bf6d,0x3f0ebec4,0xbf0e3ec4,0x3f55bf6d,0x3f0ebf35,0x3f55bf35,0xbf553f35,0x3f0ebf35,
0x3e48bec4,0x3f7bbf6d,0xbf7b3f6d,0x3e48bec4,0xbdc90000,0x3f7fbf80,0xbf463f35,0x3f22bf35,0xbe953e48,0x3f75bf7b,0xbf623f55,0x3ef1bf0e,
0xbef13ec4,0x3f62bf6d,0xbf753f6d,0x3e95bec4,0xbf223f0e,0x3f46bf55,0xbf7f3f7b,0x3dc9be48,0x3f803f80,0xbf353f35,0x3f803f80,0xbf353f35,
0x3f803f80,0xbf353f35,0x3f803f80,0xbf353f35,0x3f803f80,0xbf353f35,0x3f803f80,0xbf353f35,0x3f803f80,0xbf353f35,0x3f803f80,0xbf353f35,
0x3f7e3f80,0xbdfbbcc9,0x3f1d3f31,0xbf4abf39,0x3f733f7a,0xbea1be60,0x3ee63f09,0xbf65bf58,0x3f5f3f6a,0xbefcbecf,0x3e893eb8,0xbf77bf6f,
0x3f423f51,0xbf27bf13,0x3d973e2f,0xbf7fbf7c,0x3f783f80,0xbe79bd49,0xbe79bd49,0xbf78bf80,0x3f4e3f67,0xbf18bedb,0xbf18bedb,0xbf4ebf67,
0x3f043f2c,0xbf5cbf3e,0xbf5cbf3e,0xbf04bf2c,0x3e163eac,0xbf7dbf71,0xbf7dbf71,0xbe16beac,0x3f6f3f7f,0xbeb8bd97,0xbf6abf42,0xbecfbf27,
0x3f133f4a,0xbf51bf1d,0xbf7cbf7e,0x3e2fbdfb,0x3cc93ea1,0xbf80bf73,0xbf39bf65,0x3f313ee6,0xbf09be89,0xbf58bf77,0xbe60befc,0x3f7a3f5f,
0x3f623f7f,0xbef1bdc9,0xbf62bf7f,0x3ef13dc9,0x3e953f22,0xbf75bf46,0xbe95bf22,0x3f753f46,0xbef1bdc9,0xbf62bf7f,0x3ef13dc9,0x3f623f7f,
0xbf75bf46,0xbe95bf22,0x3f753f46,0x3e953f22,0x3f513f7e,0xbf13bdfb,0xbe2fbf1d,0x3f7c3f4a,0xbcc93ee6,0xbf80bf65,0x3f393ea1,0x3f313f73,
0xbf58befc,0xbf09bf5f,0x3f7a3f77,0xbe603e89,0xbf6abf7f,0x3ecfbd97,0x3eb83f42,0xbf6fbf27,0x3f3e3f7d,0xbf2cbe16,0x3f2c3e16,0x3f3e3f7d,
0xbeac3e79,0xbf71bf78,0x3f713f78,0xbeac3e79,0xbf80bf4e,0xbd49bf18,0x3d493f18,0xbf80bf4e,0xbedbbf5c,0x3f673f04,0xbf67bf04,0xbedbbf5c,
0x3f273f7c,0xbf42be2f,0x3f7f3f51,0xbd973f13,0xbf1d3cc9,0xbf4abf80,0x3dfb3f39,0xbf7ebf31,0xbf65bf7a,0x3ee6be60,0xbf73bf09,0xbea1bf58,
0x3e89becf,0x3f773f6a,0xbefcbf6f,0x3f5f3eb8,0x3f0e3f7b,0xbf55be48,0x3f0e3f7b,0xbf55be48,0xbf55be48,0xbf0ebf7b,0xbf55be48,0xbf0ebf7b,
0xbf0ebf7b,0x3f553e48,0xbf0ebf7b,0x3f553e48,0x3f553e48,0x3f0e3f7b,0x3f553e48,0x3f0e3f7b,0x3ee63f7a,0xbf65be60,0xbea13f09,0xbf73bf58,
0xbf77becf,0xbe89bf6a,0xbf5fbf6f,0x3efcbeb8,0xbd97bf51,0x3f7f3f13,0x3f27be2f,0x3f423f7c,0x3f7e3f39,0xbdfb3f31,0x3f1d3f80,0xbf4abcc9,
0x3eac3f78,0xbf71be79,0xbf71be79,0xbeacbf78,0xbf80bf18,0x3d49bf4e,0x3d49bf4e,0x3f803f18,0x3edbbf04,0x3f673f5c,0x3f673f5c,0xbedb3f04,
0x3f2c3f7d,0xbf3e3e16,0xbf3e3e16,0xbf2cbf7d,0x3e603f77,0xbf7abe89,0xbf58bf5f,0x3f09befc,0xbf6fbf42,0x3eb8bf27,0x3f6a3d97,0x3ecf3f7f,
0x3f51bdfb,0x3f133f7e,0xbe2f3f4a,0xbf7cbf1d,0x3cc93f65,0xbf80bee6,0xbf39bf73,0x3f31bea1,0x3dc93f75,0xbf7fbe95,0xbdc9bf75,0x3f7f3e95,
0xbf46bf62,0x3f22bef1,0x3f463f62,0xbf223ef1,0x3f7f3e95,0x3dc93f75,0xbf7fbe95,0xbdc9bf75,0xbf223ef1,0xbf46bf62,0x3f22bef1,0x3f463f62,
0xbcc93f73,0xbf80bea1,0x3f39bee6,0x3f313f65,0xbf09bf77,0x3f58be89,0xbe603f5f,0xbf7abefc,0x3f6a3f27,0xbecf3f42,0xbeb8bf7f,0x3f6fbd97,
0xbf7cbdfb,0xbe2fbf7e,0x3f513f4a,0xbf133f1d,0xbe163f71,0xbf7dbeac,0x3f7d3eac,0xbe163f71,0xbe79bf80,0x3f78bd49,0xbf783d49,0xbe79bf80,
0x3f183f67,0xbf4e3edb,0x3f4ebedb,0x3f183f67,0xbf5cbf2c,0x3f04bf3e,0xbf043f3e,0xbf5cbf2c,0xbe893f6f,0xbf77beb8,0x3efc3f6a,0xbf5f3ecf,
0x3d97bf7c,0x3f7f3e2f,0xbf27bf51,0x3f42bf13,0x3dfb3f80,0xbf7e3cc9,0x3f4a3f31,0xbf1d3f39,0xbea1bf7a,0x3f73be60,0xbf65bf09,0x3ee6bf58,
0xbec43f6d,0xbf6dbec4,0xbec43f6d,0xbf6dbec4,0x3ec4bf6d,0x3f6d3ec4,0x3ec4bf6d,0x3f6d3ec4,0xbec43f6d,0xbf6dbec4,0xbec43f6d,0xbf6dbec4,
0x3ec4bf6d,0x3f6d3ec4,0x3ec4bf6d,0x3f6d3ec4,0xbefc3f6a,0xbf5fbecf,0xbf773eb8,0xbe89bf6f,0x3f27bf51,0x3f423f13,0x3f7fbe2f,0x3d973f7c,
0xbf4a3f31,0xbf1dbf39,0xbf7ebcc9,0x3dfbbf80,0x3f65bf09,0x3ee63f58,0x3f733e60,0xbea13f7a,0xbf183f67,0xbf4ebedb,0xbf4ebedb,0x3f18bf67,
0x3f5cbf2c,0x3f043f3e,0x3f043f3e,0xbf5c3f2c,0xbf7d3eac,0xbe16bf71,0xbe16bf71,0x3f7dbeac,0x3f783d49,0xbe793f80,0xbe793f80,0xbf78bd49,
0xbf313f65,0xbf39bee6,0xbcc9bf73,0x3f80bea1,0x3f7abefc,0x3e603f5f,0xbf093f77,0xbf58be89,0xbf6fbd97,0x3eb8bf7f,0x3f6abf27,0x3ecf3f42,
0x3f133f1d,0xbf513f4a,0xbf7c3dfb,0x3e2fbf7e,0xbf463f62,0xbf22bef1,0x3f46bf62,0x3f223ef1,0x3f7fbe95,0xbdc93f75,0xbf7f3e95,0x3dc9bf75,
0xbf22bef1,0x3f46bf62,0x3f223ef1,0xbf463f62,0xbdc93f75,0xbf7f3e95,0x3dc9bf75,0x3f7fbe95,0xbf583f5f,0xbf09befc,0x3f7abe89,0xbe603f77,
0x3f6abd97,0xbecf3f7f,0xbeb8bf27,0x3f6fbf42,0xbe2fbf4a,0x3f7cbf1d,0xbf133f7e,0xbf51bdfb,0xbf393f73,0xbf31bea1,0x3f80bee6,0xbcc93f65,
0xbf673f5c,0xbedbbf04,0x3edb3f04,0xbf673f5c,0x3f3e3e16,0xbf2c3f7d,0x3f2cbf7d,0x3f3e3e16,0x3eacbf78,0x3f71be79,0xbf713e79,0x3eacbf78,
0xbf803f18,0xbd49bf4e,0x3d493f4e,0xbf803f18,0xbf733f58,0xbea1bf09,0xbee63f7a,0xbf653e60,0x3efc3eb8,0xbf5f3f6f,0x3f77becf,0xbe893f6a,
0x3f42bf7c,0x3f273e2f,0x3d97bf51,0x3f7fbf13,0xbf4a3cc9,0x3f1dbf80,0xbf7e3f39,0xbdfbbf31,0xbf7b3f55,0xbe48bf0e,0xbf7b3f55,0xbe48bf0e,
0x3e483f0e,0xbf7b3f55,0x3e483f0e,0xbf7b3f55,0x3f7bbf55,0x3e483f0e,0x3f7bbf55,0x3e483f0e,0xbe48bf0e,0x3f7bbf55,0xbe48bf0e,0x3f7bbf55,
0xbf7f3f51,0xbd97bf13,0xbf423e2f,0x3f27bf7c,0xbdfb3f39,0xbf7e3f31,0xbf4a3f80,0xbf1dbcc9,0x3f73bf09,0xbea13f58,0x3ee63e60,0xbf653f7a,
0x3efcbf6f,0x3f5fbeb8,0x3f77bf6a,0x3e893ecf,0xbf803f4e,0x3d49bf18,0x3d49bf18,0x3f80bf4e,0xbedb3f5c,0xbf673f04,0xbf673f04,0x3edbbf5c,
0x3f2cbe16,0xbf3e3f7d,0xbf3e3f7d,0xbf2c3e16,0x3f71bf78,0x3eac3e79,0x3eac3e79,0xbf713f78,0xbf7c3f4a,0x3e2fbf1d,0x3f51bf7e,0x3f13bdfb,
0xbf313f73,0xbf393ea1,0xbcc9bee6,0x3f80bf65,0x3e603e89,0xbf7a3f77,0xbf583efc,0x3f09bf5f,0x3f6fbf27,0xbeb83f42,0xbf6a3f7f,0xbecfbd97,
0xbf753f46,0x3e95bf22,0x3f75bf46,0xbe953f22,0xbf623f7f,0xbef13dc9,0x3f62bf7f,0x3ef1bdc9,0xbe953f22,0xbf753f46,0x3e95bf22,0x3f75bf46,
0x3ef1bdc9,0xbf623f7f,0xbef13dc9,0x3f62bf7f,0xbf6a3f42,0x3ecfbf27,0x3eb8bd97,0xbf6f3f7f,0xbf7c3f7e,0xbe2fbdfb,0x3f51bf1d,0xbf133f4a,
0xbf393f65,0xbf313ee6,0x3f80bf73,0xbcc93ea1,0xbe603efc,0xbf7a3f5f,0x3f58bf77,0x3f09be89,0xbf5c3f3e,0x3f04bf2c,0xbf043f2c,0xbf5c3f3e,
0xbf7d3f71,0x3e16beac,0xbe163eac,0xbf7d3f71,0xbf783f80,0xbe793d49,0x3e79bd49,0xbf783f80,0xbf4e3f67,0xbf183edb,0x3f18bedb,0xbf4e3f67,
0xbf4a3f39,0x3f1dbf31,0xbf7e3f80,0xbdfb3cc9,0xbf653f58,0x3ee6bf09,0xbf733f7a,0xbea13e60,0xbf773f6f,0x3e89beb8,0xbf5f3f6a,0xbefc3ecf,
0xbf7f3f7c,0x3d97be2f,0xbf423f51,0xbf273f13,0x3f803f80,0xbf353f35,0x3f803f80,0xbf353f35,0x3f803f80,0xbf353f35,0x3f803f80,0xbf353f35,
0x3f803f80,0xbf353f35,0x3f803f80,0xbf353f35,0x3f803f80,0xbf353f35,0x3f803f80,0xbf353f35,0xbdfbbcc9,0xbf7ebf80,0xbf4abf39,0xbf1dbf31,
0xbea1be60,0xbf73bf7a,0xbf65bf58,0xbee6bf09,0xbefcbecf,0xbf5fbf6a,0xbf77bf6f,0xbe89beb8,0xbf27bf13,0xbf42bf51,0xbf7fbf7c,0xbd97be2f,
0xbf78bf80,0x3e793d49,0x3e793d49,0x3f783f80,0xbf4ebf67,0x3f183edb,0x3f183edb,0x3f4e3f67,0xbf04bf2c,0x3f5c3f3e,0x3f5c3f3e,0x3f043f2c,
0xbe16beac,0x3f7d3f71,0x3f7d3f71,0x3e163eac,0x3eb83d97,0x3f6f3f7f,0x3ecf3f27,0xbf6abf42,0x3f513f1d,0x3f133f4a,0xbe2f3dfb,0xbf7cbf7e,
0x3f803f73,0x3cc93ea1,0xbf31bee6,0xbf39bf65,0x3f583f77,0xbf09be89,0xbf7abf5f,0xbe60befc,0x3f623f7f,0xbef1bdc9,0xbf62bf7f,0x3ef13dc9,
0x3e953f22,0xbf75bf46,0xbe95bf22,0x3f753f46,0xbef1bdc9,0xbf62bf7f,0x3ef13dc9,0x3f623f7f,0xbf75bf46,0xbe95bf22,0x3f753f46,0x3e953f22,
0xbf13bdfb,0xbf51bf7e,0x3f7c3f4a,0x3e2f3f1d,0xbf80bf65,0x3cc9bee6,0x3f313f73,0xbf39bea1,0xbf09bf5f,0x3f583efc,0xbe603e89,0xbf7abf77,
0x3ecfbd97,0x3f6a3f7f,0xbf6fbf27,0xbeb8bf42,0xbf3ebf7d,0x3f2c3e16,0xbf2cbe16,0xbf3ebf7d,0x3eacbe79,0x3f713f78,0xbf71bf78,0x3eacbe79,
0x3f803f4e,0x3d493f18,0xbd49bf18,0x3f803f4e,0x3edb3f5c,0xbf67bf04,0x3f673f04,0x3edb3f5c,0x3f423e2f,0x3f273f7c,0x3d97bf13,0x3f7f3f51,
0x3f4a3f80,0xbf1d3cc9,0x3f7e3f31,0x3dfb3f39,0xbee63e60,0xbf65bf7a,0x3ea13f58,0xbf73bf09,0xbf77bf6a,0x3e89becf,0xbf5fbeb8,0xbefcbf6f,
0x3f0e3f7b,0xbf55be48,0x3f0e3f7b,0xbf55be48,0xbf55be48,0xbf0ebf7b,0xbf55be48,0xbf0ebf7b,0xbf0ebf7b,0x3f553e48,0xbf0ebf7b,0x3f553e48,
0x3f553e48,0x3f0e3f7b,0x3f553e48,0x3f0e3f7b,0xbf65be60,0xbee6bf7a,0xbf73bf58,0x3ea1bf09,0xbe89bf6a,0x3f773ecf,0x3efcbeb8,0x3f5f3f6f,
0x3f7f3f13,0x3d973f51,0x3f423f7c,0xbf273e2f,0xbdfb3f31,0xbf7ebf39,0xbf4abcc9,0xbf1dbf80,0xbeacbf78,0x3f713e79,0x3f713e79,0x3eac3f78,
0x3f803f18,0xbd493f4e,0xbd493f4e,0xbf80bf18,0xbedb3f04,0xbf67bf5c,0xbf67bf5c,0x3edbbf04,0xbf2cbf7d,0x3f3ebe16,0x3f3ebe16,0x3f2c3f7d,
0x3f7a3e89,0x3e603f77,0xbf093efc,0xbf58bf5f,0xbeb83f27,0xbf6fbf42,0xbecfbf7f,0x3f6a3d97,0xbf13bf7e,0x3f51bdfb,0x3f7c3f1d,0xbe2f3f4a,
0x3f803ee6,0x3cc93f65,0xbf313ea1,0xbf39bf73,0x3dc93f75,0xbf7fbe95,0xbdc9bf75,0x3f7f3e95,0xbf46bf62,0x3f22bef1,0x3f463f62,0xbf223ef1,
0x3f7f3e95,0x3dc93f75,0xbf7fbe95,0xbdc9bf75,0xbf223ef1,0xbf46bf62,0x3f22bef1,0x3f463f62,0xbf80bea1,0x3cc9bf73,0x3f313f65,0xbf393ee6,
0x3f58be89,0x3f093f77,0xbf7abefc,0x3e60bf5f,0xbecf3f42,0xbf6abf27,0x3f6fbd97,0x3eb83f7f,0xbe2fbf7e,0x3f7c3dfb,0xbf133f1d,0xbf51bf4a,
0x3e16bf71,0x3f7d3eac,0xbf7dbeac,0x3e16bf71,0x3e793f80,0xbf783d49,0x3f78bd49,0x3e793f80,0xbf18bf67,0x3f4ebedb,0xbf4e3edb,0xbf18bf67,
0x3f5c3f2c,0xbf043f3e,0x3f04bf3e,0x3f5c3f2c,0x3f773eb8,0xbe893f6f,0x3f5fbecf,0x3efc3f6a,0xbf7fbe2f,0x3d97bf7c,0xbf423f13,0xbf27bf51,
0x3f7ebcc9,0x3dfb3f80,0x3f1dbf39,0x3f4a3f31,0xbf733e60,0xbea1bf7a,0xbee63f58,0xbf65bf09,0xbec43f6d,0xbf6dbec4,0xbec43f6d,0xbf6dbec4,
0x3ec4bf6d,0x3f6d3ec4,0x3ec4bf6d,0x3f6d3ec4,0xbec43f6d,0xbf6dbec4,0xbec43f6d,0xbf6dbec4,0x3ec4bf6d,0x3f6d3ec4,0x3ec4bf6d,0x3f6d3ec4,
0xbf5fbecf,0x3efcbf6a,0xbe89bf6f,0x3f77beb8,0x3f423f13,0xbf273f51,0x3d973f7c,0xbf7f3e2f,0xbf1dbf39,0x3f4abf31,0x3dfbbf80,0x3f7e3cc9,
0x3ee63f58,0xbf653f09,0xbea13f7a,0xbf73be60,0x3f18bf67,0x3f4e3edb,0x3f4e3edb,0xbf183f67,0xbf5c3f2c,0xbf04bf3e,0xbf04bf3e,0x3f5cbf2c,
0x3f7dbeac,0x3e163f71,0x3e163f71,0xbf7d3eac,0xbf78bd49,0x3e79bf80,0x3e79bf80,0x3f783d49,0x3f393ee6,0xbf313f65,0xbf803ea1,0xbcc9bf73,
0xbe60bf5f,0x3f7abefc,0x3f583e89,0xbf093f77,0xbeb83f7f,0xbf6fbd97,0xbecfbf42,0x3f6abf27,0x3f51bf4a,0x3f133f1d,0xbe2f3f7e,0xbf7c3dfb,
0xbf463f62,0xbf22bef1,0x3f46bf62,0x3f223ef1,0x3f7fbe95,0xbdc93f75,0xbf7f3e95,0x3dc9bf75,0xbf22bef1,0x3f46bf62,0x3f223ef1,0xbf463f62,
0xbdc93f75,0xbf7f3e95,0x3dc9bf75,0x3f7fbe95,0xbf09befc,0x3f58bf5f,0xbe603f77,0xbf7a3e89,0xbecf3f7f,0xbf6a3d97,0x3f6fbf42,0x3eb83f27,
0x3f7cbf1d,0x3e2f3f4a,0xbf51bdfb,0x3f13bf7e,0xbf31bea1,0x3f39bf73,0xbcc93f65,0xbf803ee6,0x3f67bf5c,0x3edb3f04,0xbedbbf04,0x3f67bf5c,
0xbf3ebe16,0x3f2cbf7d,0xbf2c3f7d,0xbf3ebe16,0xbeac3f78,0xbf713e79,0x3f71be79,0xbeac3f78,0x3f80bf18,0x3d493f4e,0xbd49bf4e,0x3f80bf18,
0x3ea13f09,0xbf733f58,0x3f65be60,0xbee63f7a,0x3f5fbf6f,0x3efc3eb8,0x3e89bf6a,0x3f77becf,0xbf27be2f,0x3f42bf7c,0xbf7f3f13,0x3d97bf51,
0xbf1d3f80,0xbf4a3cc9,0x3dfb3f31,0xbf7e3f39,0xbf7b3f55,0xbe48bf0e,0xbf7b3f55,0xbe48bf0e,0x3e483f0e,0xbf7b3f55,0x3e483f0e,0xbf7b3f55,
0x3f7bbf55,0x3e483f0e,0x3f7bbf55,0x3e483f0e,0xbe48bf0e,0x3f7bbf55,0xbe48bf0e,0x3f7bbf55,0xbd97bf13,0x3f7fbf51,0x3f27bf7c,0x3f42be2f,
0xbf7e3f31,0x3dfbbf39,0xbf1dbcc9,0x3f4abf80,0xbea13f58,0xbf733f09,0xbf653f7a,0xbee6be60,0x3f5fbeb8,0xbefc3f6f,0x3e893ecf,0xbf773f6a,
0x3f80bf4e,0xbd493f18,0xbd493f18,0xbf803f4e,0x3edbbf5c,0x3f67bf04,0x3f67bf04,0xbedb3f5c,0xbf2c3e16,0x3f3ebf7d,0x3f3ebf7d,0x3f2cbe16,
0xbf713f78,0xbeacbe79,0xbeacbe79,0x3f71bf78,0xbe2f3f1d,0xbf7c3f4a,0xbf133dfb,0x3f51bf7e,0x3f39bea1,0xbf313f73,0xbf803f65,0xbcc9bee6,
0x3f7abf77,0x3e603e89,0xbf093f5f,0xbf583efc,0x3eb8bf42,0x3f6fbf27,0x3ecf3d97,0xbf6a3f7f,0xbf753f46,0x3e95bf22,0x3f75bf46,0xbe953f22,
0xbf623f7f,0xbef13dc9,0x3f62bf7f,0x3ef1bdc9,0xbe953f22,0xbf753f46,0x3e95bf22,0x3f75bf46,0x3ef1bdc9,0xbf623f7f,0xbef13dc9,0x3f62bf7f,
0x3ecfbf27,0x3f6abf42,0xbf6f3f7f,0xbeb83d97,0xbe2fbdfb,0x3f7cbf7e,0xbf133f4a,0xbf513f1d,0xbf313ee6,0x3f39bf65,0xbcc93ea1,0xbf803f73,
0xbf7a3f5f,0x3e60befc,0x3f09be89,0xbf583f77,0x3f5cbf3e,0xbf043f2c,0x3f04bf2c,0x3f5cbf3e,0x3f7dbf71,0xbe163eac,0x3e16beac,0x3f7dbf71,
0x3f78bf80,0x3e79bd49,0xbe793d49,0x3f78bf80,0x3f4ebf67,0x3f18bedb,0xbf183edb,0x3f4ebf67,0xbf1d3f31,0xbf4a3f39,0x3dfbbcc9,0xbf7e3f80,
0xbee63f09,0xbf653f58,0x3ea1be60,0xbf733f7a,0xbe893eb8,0xbf773f6f,0x3efcbecf,0xbf5f3f6a,0xbd973e2f,0xbf7f3f7c,0x3f27bf13,0xbf423f51,
0x3f803f80,0xbf353f35,0x3f803f80,0xbf353f35,0x3f803f80,0xbf353f35,0x3f803f80,0xbf353f35,0x3f803f80,0xbf353f35,0x3f803f80,0xbf353f35,
0x3f803f80,0xbf353f35,0x3f803f80,0xbf353f35,0xbf7ebf80,0x3dfb3cc9,0xbf1dbf31,0x3f4a3f39,0xbf73bf7a,0x3ea13e60,0xbee6bf09,0x3f653f58,
0xbf5fbf6a,0x3efc3ecf,0xbe89beb8,0x3f773f6f,0xbf42bf51,0x3f273f13,0xbd97be2f,0x3f7f3f7c,0x3f783f80,0xbe79bd49,0xbe79bd49,0xbf78bf80,
0x3f4e3f67,0xbf18bedb,0xbf18bedb,0xbf4ebf67,0x3f043f2c,0xbf5cbf3e,0xbf5cbf3e,0xbf04bf2c,0x3e163eac,0xbf7dbf71,0xbf7dbf71,0xbe16beac,
0xbf6fbf7f,0x3eb83d97,0x3f6a3f42,0x3ecf3f27,0xbf13bf4a,0x3f513f1d,0x3f7c3f7e,0xbe2f3dfb,0xbcc9bea1,0x3f803f73,0x3f393f65,0xbf31bee6,
0x3f093e89,0x3f583f77,0x3e603efc,0xbf7abf5f,0x3f623f7f,0xbef1bdc9,0xbf62bf7f,0x3ef13dc9,0x3e953f22,0xbf75bf46,0xbe95bf22,0x3f753f46,
0xbef1bdc9,0xbf62bf7f,0x3ef13dc9,0x3f623f7f,0xbf75bf46,0xbe95bf22,0x3f753f46,0x3e953f22,0xbf51bf7e,0x3f133dfb,0x3e2f3f1d,0xbf7cbf4a,
0x3cc9bee6,0x3f803f65,0xbf39bea1,0xbf31bf73,0x3f583efc,0x3f093f5f,0xbf7abf77,0x3e60be89,0x3f6a3f7f,0xbecf3d97,0xbeb8bf42,0x3f6f3f27,
0x3f3e3f7d,0xbf2cbe16,0x3f2c3e16,0x3f3e3f7d,0xbeac3e79,0xbf71bf78,0x3f713f78,0xbeac3e79,0xbf80bf4e,0xbd49bf18,0x3d493f18,0xbf80bf4e,
0xbedbbf5c,0x3f673f04,0xbf67bf04,0xbedbbf5c,0xbf27bf7c,0x3f423e2f,0xbf7fbf51,0x3d97bf13,0x3f1dbcc9,0x3f4a3f80,0xbdfbbf39,0x3f7e3f31,
0x3f653f7a,0xbee63e60,0x3f733f09,0x3ea13f58,0xbe893ecf,0xbf77bf6a,0x3efc3f6f,0xbf5fbeb8,0x3f0e3f7b,0xbf55be48,0x3f0e3f7b,0xbf55be48,
0xbf55be48,0xbf0ebf7b,0xbf55be48,0xbf0ebf7b,0xbf0ebf7b,0x3f553e48,0xbf0ebf7b,0x3f553e48,0x3f553e48,0x3f0e3f7b,0x3f553e48,0x3f0e3f7b,
0xbee6bf7a,0x3f653e60,0x3ea1bf09,0x3f733f58,0x3f773ecf,0x3e893f6a,0x3f5f3f6f,0xbefc3eb8,0x3d973f51,0xbf7fbf13,0xbf273e2f,0xbf42bf7c,
0xbf7ebf39,0x3dfbbf31,0xbf1dbf80,0x3f4a3cc9,0x3eac3f78,0xbf71be79,0xbf71be79,0xbeacbf78,0xbf80bf18,0x3d49bf4e,0x3d49bf4e,0x3f803f18,
0x3edbbf04,0x3f673f5c,0x3f673f5c,0xbedb3f04,0x3f2c3f7d,0xbf3e3e16,0xbf3e3e16,0xbf2cbf7d,0xbe60bf77,0x3f7a3e89,0x3f583f5f,0xbf093efc,
0x3f6f3f42,0xbeb83f27,0xbf6abd97,0xbecfbf7f,0xbf513dfb,0xbf13bf7e,0x3e2fbf4a,0x3f7c3f1d,0xbcc9bf65,0x3f803ee6,0x3f393f73,0xbf313ea1,
0x3dc93f75,0xbf7fbe95,0xbdc9bf75,0x3f7f3e95,0xbf46bf62,0x3f22bef1,0x3f463f62,0xbf223ef1,0x3f7f3e95,0x3dc93f75,0xbf7fbe95,0xbdc9bf75,
0xbf223ef1,0xbf46bf62,0x3f22bef1,0x3f463f62,0x3cc9bf73,0x3f803ea1,0xbf393ee6,0xbf31bf65,0x3f093f77,0xbf583e89,0x3e60bf5f,0x3f7a3efc,
0xbf6abf27,0x3ecfbf42,0x3eb83f7f,0xbf6f3d97,0x3f7c3dfb,0x3e2f3f7e,0xbf51bf4a,0x3f13bf1d,0xbe163f71,0xbf7dbeac,0x3f7d3eac,0xbe163f71,
0xbe79bf80,0x3f78bd49,0xbf783d49,0xbe79bf80,0x3f183f67,0xbf4e3edb,0x3f4ebedb,0x3f183f67,0xbf5cbf2c,0x3f04bf3e,0xbf043f3e,0xbf5cbf2c,
0x3e89bf6f,0x3f773eb8,0xbefcbf6a,0x3f5fbecf,0xbd973f7c,0xbf7fbe2f,0x3f273f51,0xbf423f13,0xbdfbbf80,0x3f7ebcc9,0xbf4abf31,0x3f1dbf39,
0x3ea13f7a,0xbf733e60,0x3f653f09,0xbee63f58,0xbec43f6d,0xbf6dbec4,0xbec43f6d,0xbf6dbec4,0x3ec4bf6d,0x3f6d3ec4,0x3ec4bf6d,0x3f6d3ec4,
0xbec43f6d,0xbf6dbec4,0xbec43f6d,0xbf6dbec4,0x3ec4bf6d,0x3f6d3ec4,0x3ec4bf6d,0x3f6d3ec4,0x3efcbf6a,0x3f5f3ecf,0x3f77beb8,0x3e893f6f,
0xbf273f51,0xbf42bf13,0xbf7f3e2f,0xbd97bf7c,0x3f4abf31,0x3f1d3f39,0x3f7e3cc9,0xbdfb3f80,0xbf653f09,0xbee6bf58,0xbf73be60,0x3ea1bf7a,
0xbf183f67,0xbf4ebedb,0xbf4ebedb,0x3f18bf67,0x3f5cbf2c,0x3f043f3e,0x3f043f3e,0xbf5c3f2c,0xbf7d3eac,0xbe16bf71,0xbe16bf71,0x3f7dbeac,
0x3f783d49,0xbe793f80,0xbe793f80,0xbf78bd49,0x3f31bf65,0x3f393ee6,0x3cc93f73,0xbf803ea1,0xbf7a3efc,0xbe60bf5f,0x3f09bf77,0x3f583e89,
0x3f6f3d97,0xbeb83f7f,0xbf6a3f27,0xbecfbf42,0xbf13bf1d,0x3f51bf4a,0x3f7cbdfb,0xbe2f3f7e,0xbf463f62,0xbf22bef1,0x3f46bf62,0x3f223ef1,
0x3f7fbe95,0xbdc93f75,0xbf7f3e95,0x3dc9bf75,0xbf22bef1,0x3f46bf62,0x3f223ef1,0xbf463f62,0xbdc93f75,0xbf7f3e95,0x3dc9bf75,0x3f7fbe95,
0x3f58bf5f,0x3f093efc,0xbf7a3e89,0x3e60bf77,0xbf6a3d97,0x3ecfbf7f,0x3eb83f27,0xbf6f3f42,0x3e2f3f4a,0xbf7c3f1d,0x3f13bf7e,0x3f513dfb,
0x3f39bf73,0x3f313ea1,0xbf803ee6,0x3cc9bf65,0xbf673f5c,0xbedbbf04,0x3edb3f04,0xbf673f5c,0x3f3e3e16,0xbf2c3f7d,0x3f2cbf7d,0x3f3e3e16,
0x3eacbf78,0x3f71be79,0xbf713e79,0x3eacbf78,0xbf803f18,0xbd49bf4e,0x3d493f4e,0xbf803f18,0x3f73bf58,0x3ea13f09,0x3ee6bf7a,0x3f65be60,
0xbefcbeb8,0x3f5fbf6f,0xbf773ecf,0x3e89bf6a,0xbf423f7c,0xbf27be2f,0xbd973f51,0xbf7f3f13,0x3f4abcc9,0xbf1d3f80,0x3f7ebf39,0x3dfb3f31,
0xbf7b3f55,0xbe48bf0e,0xbf7b3f55,0xbe48bf0e,0x3e483f0e,0xbf7b3f55,0x3e483f0e,0xbf7b3f55,0x3f7bbf55,0x3e483f0e,0x3f7bbf55,0x3e483f0e,
0xbe48bf0e,0x3f7bbf55,0xbe48bf0e,0x3f7bbf55,0x3f7fbf51,0x3d973f13,0x3f42be2f,0xbf273f7c,0x3dfbbf39,0x3f7ebf31,0x3f4abf80,0x3f1d3cc9,
0xbf733f09,0x3ea1bf58,0xbee6be60,0x3f65bf7a,0xbefc3f6f,0xbf5f3eb8,0xbf773f6a,0xbe89becf,0xbf803f4e,0x3d49bf18,0x3d49bf18,0x3f80bf4e,
0xbedb3f5c,0xbf673f04,0xbf673f04,0x3edbbf5c,0x3f2cbe16,0xbf3e3f7d,0xbf3e3f7d,0xbf2c3e16,0x3f71bf78,0x3eac3e79,0x3eac3e79,0xbf713f78,
0x3f7cbf4a,0xbe2f3f1d,0xbf513f7e,0xbf133dfb,0x3f31bf73,0x3f39bea1,0x3cc93ee6,0xbf803f65,0xbe60be89,0x3f7abf77,0x3f58befc,0xbf093f5f,
0xbf6f3f27,0x3eb8bf42,0x3f6abf7f,0x3ecf3d97,0xbf753f46,0x3e95bf22,0x3f75bf46,0xbe953f22,0xbf623f7f,0xbef13dc9,0x3f62bf7f,0x3ef1bdc9,
0xbe953f22,0xbf753f46,0x3e95bf22,0x3f75bf46,0x3ef1bdc9,0xbf623f7f,0xbef13dc9,0x3f62bf7f,0x3f6abf42,0xbecf3f27,0xbeb83d97,0x3f6fbf7f,
0x3f7cbf7e,0x3e2f3dfb,0xbf513f1d,0x3f13bf4a,0x3f39bf65,0x3f31bee6,0xbf803f73,0x3cc9bea1,0x3e60befc,0x3f7abf5f,0xbf583f77,0xbf093e89,
0xbf5c3f3e,0x3f04bf2c,0xbf043f2c,0xbf5c3f3e,0xbf7d3f71,0x3e16beac,0xbe163eac,0xbf7d3f71,0xbf783f80,0xbe793d49,0x3e79bd49,0xbf783f80,
0xbf4e3f67,0xbf183edb,0x3f18bedb,0xbf4e3f67,0x3f4abf39,0xbf1d3f31,0x3f7ebf80,0x3dfbbcc9,0x3f65bf58,0xbee63f09,0x3f73bf7a,0x3ea1be60,
0x3f77bf6f,0xbe893eb8,0x3f5fbf6a,0x3efcbecf,0x3f7fbf7c,0xbd973e2f,0x3f42bf51,0x3f27bf13,0x3f803f80,0xbf353f35,0x3f803f80,0xbf353f35,
0x3f803f80,0xbf353f35,0x3f803f80,0xbf353f35,0x3f803f80,0xbf353f35,0x3f803f80,0xbf353f35,0x3f803f80,0xbf353f35,0x3f803f80,0xbf353f35,
0x3dfb3cc9,0x3f7e3f80,0x3f4a3f39,0x3f1d3f31,0x3ea13e60,0x3f733f7a,0x3f653f58,0x3ee63f09,0x3efc3ecf,0x3f5f3f6a,0x3f773f6f,0x3e893eb8,
0x3f273f13,0x3f423f51,0x3f7f3f7c,0x3d973e2f,0xbf78bf80,0x3e793d49,0x3e793d49,0x3f783f80,0xbf4ebf67,0x3f183edb,0x3f183edb,0x3f4e3f67,
0xbf04bf2c,0x3f5c3f3e,0x3f5c3f3e,0x3f043f2c,0xbe16beac,0x3f7d3f71,0x3f7d3f71,0x3e163eac,0xbeb8bd97,0xbf6fbf7f,0xbecfbf27,0x3f6a3f42,
0xbf51bf1d,0xbf13bf4a,0x3e2fbdfb,0x3f7c3f7e,0xbf80bf73,0xbcc9bea1,0x3f313ee6,0x3f393f65,0xbf58bf77,0x3f093e89,0x3f7a3f5f,0x3e603efc,
0x3f623f7f,0xbef1bdc9,0xbf62bf7f,0x3ef13dc9,0x3e953f22,0xbf75bf46,0xbe95bf22,0x3f753f46,0xbef1bdc9,0xbf62bf7f,0x3ef13dc9,0x3f623f7f,
0xbf75bf46,0xbe95bf22,0x3f753f46,0x3e953f22,0x3f133dfb,0x3f513f7e,0xbf7cbf4a,0xbe2fbf1d,0x3f803f65,0xbcc93ee6,0xbf31bf73,0x3f393ea1,
0x3f093f5f,0xbf58befc,0x3e60be89,0x3f7a3f77,0xbecf3d97,0xbf6abf7f,0x3f6f3f27,0x3eb83f42,0xbf3ebf7d,0x3f2c3e16,0xbf2cbe16,0xbf3ebf7d,
0x3eacbe79,0x3f713f78,0xbf71bf78,0x3eacbe79,0x3f803f4e,0x3d493f18,0xbd49bf18,0x3f803f4e,0x3edb3f5c,0xbf67bf04,0x3f673f04,0x3edb3f5c,
0xbf42be2f,0xbf27bf7c,0xbd973f13,0xbf7fbf51,0xbf4abf80,0x3f1dbcc9,0xbf7ebf31,0xbdfbbf39,0x3ee6be60,0x3f653f7a,0xbea1bf58,0x3f733f09,
0x3f773f6a,0xbe893ecf,0x3f5f3eb8,0x3efc3f6f,0x3f0e3f7b,0xbf55be48,0x3f0e3f7b,0xbf55be48,0xbf55be48,0xbf0ebf7b,0xbf55be48,0xbf0ebf7b,
0xbf0ebf7b,0x3f553e48,0xbf0ebf7b,0x3f553e48,0x3f553e48,0x3f0e3f7b,0x3f553e48,0x3f0e3f7b,0x3f653e60,0x3ee63f7a,0x3f733f58,0xbea13f09,
0x3e893f6a,0xbf77becf,0xbefc3eb8,0xbf5fbf6f,0xbf7fbf13,0xbd97bf51,0xbf42bf7c,0x3f27be2f,0x3dfbbf31,0x3f7e3f39,0x3f4a3cc9,0x3f1d3f80,
0xbeacbf78,0x3f713e79,0x3f713e79,0x3eac3f78,0x3f803f18,0xbd493f4e,0xbd493f4e,0xbf80bf18,0xbedb3f04,0xbf67bf5c,0xbf67bf5c,0x3edbbf04,
0xbf2cbf7d,0x3f3ebe16,0x3f3ebe16,0x3f2c3f7d,0xbf7abe89,0xbe60bf77,0x3f09befc,0x3f583f5f,0x3eb8bf27,0x3f6f3f42,0x3ecf3f7f,0xbf6abd97,
0x3f133f7e,0xbf513dfb,0xbf7cbf1d,0x3e2fbf4a,0xbf80bee6,0xbcc9bf65,0x3f31bea1,0x3f393f73,0x3dc93f75,0xbf7fbe95,0xbdc9bf75,0x3f7f3e95,
0xbf46bf62,0x3f22bef1,0x3f463f62,0xbf223ef1,0x3f7f3e95,0x3dc93f75,0xbf7fbe95,0xbdc9bf75,0xbf223ef1,0xbf46bf62,0x3f22bef1,0x3f463f62,
0x3f803ea1,0xbcc93f73,0xbf31bf65,0x3f39bee6,0xbf583e89,0xbf09bf77,0x3f7a3efc,0xbe603f5f,0x3ecfbf42,0x3f6a3f27,0xbf6f3d97,0xbeb8bf7f,
0x3e2f3f7e,0xbf7cbdfb,0x3f13bf1d,0x3f513f4a,0x3e16bf71,0x3f7d3eac,0xbf7dbeac,0x3e16bf71,0x3e793f80,0xbf783d49,0x3f78bd49,0x3e793f80,
0xbf18bf67,0x3f4ebedb,0xbf4e3edb,0xbf18bf67,0x3f5c3f2c,0xbf043f3e,0x3f04bf3e,0x3f5c3f2c,0xbf77beb8,0x3e89bf6f,0xbf5f3ecf,0xbefcbf6a,
0x3f7f3e2f,0xbd973f7c,0x3f42bf13,0x3f273f51,0xbf7e3cc9,0xbdfbbf80,0xbf1d3f39,0xbf4abf31,0x3f73be60,0x3ea13f7a,0x3ee6bf58,0x3f653f09,
0xbec43f6d,0xbf6dbec4,0xbec43f6d,0xbf6dbec4,0x3ec4bf6d,0x3f6d3ec4,0x3ec4bf6d,0x3f6d3ec4,0xbec43f6d,0xbf6dbec4,0xbec43f6d,0xbf6dbec4,
0x3ec4bf6d,0x3f6d3ec4,0x3ec4bf6d,0x3f6d3ec4,0x3f5f3ecf,0xbefc3f6a,0x3e893f6f,0xbf773eb8,0xbf42bf13,0x3f27bf51,0xbd97bf7c,0x3f7fbe2f,
0x3f1d3f39,0xbf4a3f31,0xbdfb3f80,0xbf7ebcc9,0xbee6bf58,0x3f65bf09,0x3ea1bf7a,0x3f733e60,0x3f18bf67,0x3f4e3edb,0x3f4e3edb,0xbf183f67,
0xbf5c3f2c,0xbf04bf3e,0xbf04bf3e,0x3f5cbf2c,0x3f7dbeac,0x3e163f71,0x3e163f71,0xbf7d3eac,0xbf78bd49,0x3e79bf80,0x3e79bf80,0x3f783d49,
0xbf39bee6,0x3f31bf65,0x3f80bea1,0x3cc93f73,0x3e603f5f,0xbf7a3efc,0xbf58be89,0x3f09bf77,0x3eb8bf7f,0x3f6f3d97,0x3ecf3f42,0xbf6a3f27,
0xbf513f4a,0xbf13bf1d,0x3e2fbf7e,0x3f7cbdfb,0xbf463f62,0xbf22bef1,0x3f46bf62,0x3f223ef1,0x3f7fbe95,0xbdc93f75,0xbf7f3e95,0x3dc9bf75,
0xbf22bef1,0x3f46bf62,0x3f223ef1,0xbf463f62,0xbdc93f75,0xbf7f3e95,0x3dc9bf75,0x3f7fbe95,0x3f093efc,0xbf583f5f,0x3e60bf77,0x3f7abe89,
0x3ecfbf7f,0x3f6abd97,0xbf6f3f42,0xbeb8bf27,0xbf7c3f1d,0xbe2fbf4a,0x3f513dfb,0xbf133f7e,0x3f313ea1,0xbf393f73,0x3cc9bf65,0x3f80bee6,
0x3f67bf5c,0x3edb3f04,0xbedbbf04,0x3f67bf5c,0xbf3ebe16,0x3f2cbf7d,0xbf2c3f7d,0xbf3ebe16,0xbeac3f78,0xbf713e79,0x3f71be79,0xbeac3f78,
0x3f80bf18,0x3d493f4e,0xbd49bf4e,0x3f80bf18,0xbea1bf09,0x3f73bf58,0xbf653e60,0x3ee6bf7a,0xbf5f3f6f,0xbefcbeb8,0xbe893f6a,0xbf773ecf,
0x3f273e2f,0xbf423f7c,0x3f7fbf13,0xbd973f51,0x3f1dbf80,0x3f4abcc9,0xbdfbbf31,0x3f7ebf39,0xbf7b3f55,0xbe48bf0e,0xbf7b3f55,0xbe48bf0e,
0x3e483f0e,0xbf7b3f55,0x3e483f0e,0xbf7b3f55,0x3f7bbf55,0x3e483f0e,0x3f7bbf55,0x3e483f0e,0xbe48bf0e,0x3f7bbf55,0xbe48bf0e,0x3f7bbf55,
0x3d973f13,0xbf7f3f51,0xbf273f7c,0xbf423e2f,0x3f7ebf31,0xbdfb3f39,0x3f1d3cc9,0xbf4a3f80,0x3ea1bf58,0x3f73bf09,0x3f65bf7a,0x3ee63e60,
0xbf5f3eb8,0x3efcbf6f,0xbe89becf,0x3f77bf6a,0x3f80bf4e,0xbd493f18,0xbd493f18,0xbf803f4e,0x3edbbf5c,0x3f67bf04,0x3f67bf04,0xbedb3f5c,
0xbf2c3e16,0x3f3ebf7d,0x3f3ebf7d,0x3f2cbe16,0xbf713f78,0xbeacbe79,0xbeacbe79,0x3f71bf78,0x3e2fbf1d,0x3f7cbf4a,0x3f13bdfb,0xbf513f7e,
0xbf393ea1,0x3f31bf73,0x3f80bf65,0x3cc93ee6,0xbf7a3f77,0xbe60be89,0x3f09bf5f,0x3f58befc,0xbeb83f42,0xbf6f3f27,0xbecfbd97,0x3f6abf7f,
0xbf753f46,0x3e95bf22,0x3f75bf46,0xbe953f22,0xbf623f7f,0xbef13dc9,0x3f62bf7f,0x3ef1bdc9,0xbe953f22,0xbf753f46,0x3e95bf22,0x3f75bf46,
0x3ef1bdc9,0xbf623f7f,0xbef13dc9,0x3f62bf7f,0xbecf3f27,0xbf6a3f42,0x3f6fbf7f,0x3eb8bd97,0x3e2f3dfb,0xbf7c3f7e,0x3f13bf4a,0x3f51bf1d,
0x3f31bee6,0xbf393f65,0x3cc9bea1,0x3f80bf73,0x3f7abf5f,0xbe603efc,0xbf093e89,0x3f58bf77,0x3f5cbf3e,0xbf043f2c,0x3f04bf2c,0x3f5cbf3e,
0x3f7dbf71,0xbe163eac,0x3e16beac,0x3f7dbf71,0x3f78bf80,0x3e79bd49,0xbe793d49,0x3f78bf80,0x3f4ebf67,0x3f18bedb,0xbf183edb,0x3f4ebf67,
0x3f1dbf31,0x3f4abf39,0xbdfb3cc9,0x3f7ebf80,0x3ee6bf09,0x3f65bf58,0xbea13e60,0x3f73bf7a,0x3e89beb8,0x3f77bf6f,0xbefc3ecf,0x3f5fbf6a,
0x3d97be2f,0x3f7fbf7c,0xbf273f13,0x3f42bf51,0x3f803f80,0xbf803f80,0x3f803f80,0xbf803f80,0x3f803f80,0xbf803f80,0x3f803f80,0xbf803f80,
0x3f803f80,0xbf803f80,0x3f803f80,0xbf803f80,0x3f803f80,0xbf803f80,0x3f803f80,0xbf803f80,0x3f7d3f80,0xbe16bd49,0x3f183f2c,0xbf4ebf3e,
0x3f713f78,0xbeacbe79,0x3edb3f04,0xbf67bf5c,0x3f5c3f67,0xbf04bedb,0x3e793eac,0xbf78bf71,0x3f3e3f4e,0xbf2cbf18,0x3d493e16,0xbf80bf7d,
0x3f753f7f,0xbe95bdc9,0xbe95bdc9,0xbf75bf7f,0x3f463f62,0xbf22bef1,0xbf22bef1,0xbf46bf62,0x3ef13f22,0xbf62bf46,0xbf62bf46,0xbef1bf22,
0x3dc93e95,0xbf7fbf75,0xbf7fbf75,0xbdc9be95,0x3f673f7d,0xbedbbe16,0xbf71bf4e,0xbeacbf18,0x3f043f3e,0xbf5cbf2c,0xbf78bf80,0x3e79bd49,
0xbd493e79,0xbf80bf78,0xbf2cbf5c,0x3f3e3f04,0xbf18beac,0xbf4ebf71,0xbe16bedb,0x3f7d3f67,0x3f553f7b,0xbf0ebe48,0xbf55bf7b,0x3f0e3e48,
0x3e483f0e,0xbf7bbf55,0xbe48bf0e,0x3f7b3f55,0xbf0ebe48,0xbf55bf7b,0x3f0e3e48,0x3f553f7b,0xbf7bbf55,0xbe48bf0e,0x3f7b3f55,0x3e483f0e,
0x3f3e3f78,0xbf2cbe79,0xbd49bf04,0x3f803f5c,0xbe163eac,0xbf7dbf71,0x3f4e3edb,0x3f183f67,0xbf67bf18,0xbedbbf4e,0x3f713f7d,0xbeac3e16,
0xbf5cbf80,0x3f043d49,0x3e793f2c,0xbf78bf3e,0x3f223f75,0xbf46be95,0x3f463e95,0x3f223f75,0xbef13dc9,0xbf62bf7f,0x3f623f7f,0xbef13dc9,
0xbf7fbf62,0x3dc9bef1,0xbdc93ef1,0xbf7fbf62,0xbe95bf46,0x3f753f22,0xbf75bf22,0xbe95bf46,0x3f043f71,0xbf5cbeac,0x3f783f67,0xbe793edb,
0xbf3ebe16,0xbf2cbf7d,0xbd493f18,0xbf80bf4e,0xbf4ebf80,0x3f18bd49,0xbf7dbf2c,0xbe16bf3e,0x3edbbe79,0x3f673f78,0xbeacbf5c,0x3f713f04,
0x3ec43f6d,0xbf6dbec4,0x3ec43f6d,0xbf6dbec4,0xbf6dbec4,0xbec4bf6d,0xbf6dbec4,0xbec4bf6d,0xbec4bf6d,0x3f6d3ec4,0xbec4bf6d,0x3f6d3ec4,
0x3f6d3ec4,0x3ec43f6d,0x3f6d3ec4,0x3ec43f6d,0x3e793f67,0xbf78bedb,0xbf043eac,0xbf5cbf71,0xbf80bf18,0xbd49bf4e,0xbf3ebf7d,0x3f2cbe16,
0x3e16bf2c,0x3f7d3f3e,0x3f4e3d49,0x3f183f80,0x3f713f5c,0xbeac3f04,0x3edb3f78,0xbf67be79,0x3dc93f62,0xbf7fbef1,0xbf7fbef1,0xbdc9bf62,
0xbf75bf46,0x3e95bf22,0x3e95bf22,0x3f753f46,0x3f22be95,0x3f463f75,0x3f463f75,0xbf223e95,0x3ef13f7f,0xbf62bdc9,0xbf62bdc9,0xbef1bf7f,
0xbd493f5c,0xbf80bf04,0xbf2cbf78,0x3f3ebe79,0xbf4ebf67,0x3f18bedb,0x3f7d3eac,0x3e163f71,0x3f713e16,0x3eac3f7d,0xbedb3f18,0xbf67bf4e,
0xbe793f3e,0xbf78bf2c,0xbf04bf80,0x3f5cbd49,0xbe483f55,0xbf7bbf0e,0x3e48bf55,0x3f7b3f0e,0xbf0ebf7b,0x3f55be48,0x3f0e3f7b,0xbf553e48,
0x3f7b3f0e,0xbe483f55,0xbf7bbf0e,0x3e48bf55,0xbf553e48,0xbf0ebf7b,0x3f55be48,0x3f0e3f7b,0xbeac3f4e,0xbf71bf18,0x3f67be16,0x3edb3f7d,
0xbe79bf80,0x3f783d49,0xbf043f2c,0xbf5cbf3e,0x3f3e3f5c,0xbf2c3f04,0xbd49bf78,0x3f803e79,0xbf7dbedb,0x3e16bf67,0x3f183f71,0xbf4e3eac,
0xbef13f46,0xbf62bf22,0x3f623f22,0xbef13f46,0x3dc9bf75,0x3f7f3e95,0xbf7fbe95,0x3dc9bf75,0x3e953f7f,0xbf753dc9,0x3f75bdc9,0x3e953f7f,
0xbf22bf62,0x3f46bef1,0xbf463ef1,0xbf22bf62,0xbf183f3e,0xbf4ebf2c,0x3e163f80,0xbf7d3d49,0x3edbbf5c,0x3f673f04,0xbeacbf78,0x3f71be79,
0xbe793f71,0xbf78beac,0x3f043f67,0xbf5c3edb,0x3d49bf7d,0x3f803e16,0xbf2cbf4e,0x3f3ebf18,0xbf353f35,0xbf35bf35,0xbf353f35,0xbf35bf35,
0x3f35bf35,0x3f353f35,0x3f35bf35,0x3f353f35,0xbf353f35,0xbf35bf35,0xbf353f35,0xbf35bf35,0x3f35bf35,0x3f353f35,0x3f35bf35,0x3f353f35,
0xbf4e3f2c,0xbf18bf3e,0xbf7dbd49,0x3e16bf80,0x3f67bf04,0x3edb3f5c,0x3f713e79,0xbeac3f78,0xbf783eac,0xbe79bf71,0xbf5cbedb,0x3f04bf67,
0x3f80be16,0x3d493f7d,0x3f3e3f18,0xbf2c3f4e,0xbf623f22,0xbef1bf46,0xbef1bf46,0x3f62bf22,0x3f7fbe95,0x3dc93f75,0x3dc93f75,0xbf7f3e95,
0xbf75bdc9,0x3e95bf7f,0x3e95bf7f,0x3f753dc9,0x3f463ef1,0xbf223f62,0xbf223f62,0xbf46bef1,0xbf713f18,0xbeacbf4e,0x3edbbf7d,0x3f673e16,
0x3f78bd49,0xbe793f80,0xbf5c3f3e,0xbf04bf2c,0xbf2cbf04,0x3f3ebf5c,0x3f80be79,0xbd493f78,0x3e163f67,0xbf7d3edb,0xbf4ebeac,0x3f18bf71,
0xbf7b3f0e,0xbe48bf55,0x3f7bbf0e,0x3e483f55,0x3f553e48,0xbf0e3f7b,0xbf55be48,0x3f0ebf7b,0xbe48bf55,0x3f7bbf0e,0x3e483f55,0xbf7b3f0e,
0xbf0e3f7b,0xbf55be48,0x3f0ebf7b,0x3f553e48,0xbf803f04,0xbd49bf5c,0x3f3e3e79,0xbf2c3f78,0x3f183edb,0xbf4e3f67,0x3e16bf71,0x3f7dbeac,
0x3eacbf7d,0x3f71be16,0xbf673f4e,0xbedbbf18,0xbf783f2c,0xbe79bf3e,0x3f5c3d49,0xbf043f80,0xbf7f3ef1,0x3dc9bf62,0xbdc93f62,0xbf7f3ef1,
0x3e953f22,0xbf753f46,0x3f75bf46,0x3e953f22,0x3f46bf75,0x3f223e95,0xbf22be95,0x3f46bf75,0xbf623dc9,0x3ef1bf7f,0xbef13f7f,0xbf623dc9,
0xbf783edb,0x3e79bf67,0xbf5c3f71,0xbf04beac,0xbd493f4e,0xbf803f18,0x3f2c3e16,0xbf3e3f7d,0x3f7dbf3e,0x3e163f2c,0x3f18bf80,0x3f4ebd49,
0xbeacbf04,0x3f71bf5c,0xbf673e79,0x3edbbf78,0xbf6d3ec4,0x3ec4bf6d,0xbf6d3ec4,0x3ec4bf6d,0xbec43f6d,0xbf6d3ec4,0xbec43f6d,0xbf6d3ec4,
0x3f6dbec4,0xbec43f6d,0x3f6dbec4,0xbec43f6d,0x3ec4bf6d,0x3f6dbec4,0x3ec4bf6d,0x3f6dbec4,0xbf5c3eac,0x3f04bf71,0xbe79bedb,0x3f78bf67,
0xbf2c3f7d,0xbf3e3e16,0xbf803f4e,0xbd49bf18,0x3f183d49,0xbf4e3f80,0xbe163f3e,0xbf7d3f2c,0x3f67bf78,0x3edb3e79,0x3f71bf04,0xbeac3f5c,
0xbf463e95,0x3f22bf75,0x3f22bf75,0x3f46be95,0xbf623f7f,0xbef1bdc9,0xbef1bdc9,0x3f62bf7f,0x3dc93ef1,0xbf7f3f62,0xbf7f3f62,0xbdc9bef1,
0x3f75bf22,0xbe953f46,0xbe953f46,0xbf753f22,0xbf2c3e79,0x3f3ebf78,0x3f80bf5c,0xbd493f04,0xbf7d3f71,0xbe16beac,0x3f18bf67,0x3f4ebedb,
0xbedb3f4e,0xbf673f18,0xbeacbe16,0x3f71bf7d,0x3f04bd49,0xbf5c3f80,0xbf783f3e,0x3e79bf2c,0xbf0e3e48,0x3f55bf7b,0x3f0ebe48,0xbf553f7b,
0xbf7b3f55,0x3e48bf0e,0x3f7bbf55,0xbe483f0e,0xbf553f7b,0xbf0e3e48,0x3f55bf7b,0x3f0ebe48,0xbe483f0e,0xbf7b3f55,0x3e48bf0e,0x3f7bbf55,
0xbedb3e16,0x3f67bf7d,0xbeac3f18,0xbf713f4e,0xbf5c3f2c,0x3f04bf3e,0x3e793d49,0xbf783f80,0xbf803f78,0xbd49be79,0x3f3ebf04,0xbf2c3f5c,
0xbf4e3f71,0xbf183eac,0x3f7dbf67,0xbe163edb,0xbe953dc9,0x3f75bf7f,0xbf753f7f,0xbe953dc9,0xbf223ef1,0x3f46bf62,0xbf463f62,0xbf223ef1,
0xbf623f46,0x3ef1bf22,0xbef13f22,0xbf623f46,0xbf7f3f75,0x3dc9be95,0xbdc93e95,0xbf7f3f75,0xbe163d49,0x3f7dbf80,0xbf4e3f3e,0x3f18bf2c,
0xbeac3e79,0x3f71bf78,0xbf673f5c,0x3edbbf04,0xbf043edb,0x3f5cbf67,0xbf783f71,0x3e79beac,0xbf2c3f18,0x3f3ebf4e,0xbf803f7d,0x3d49be16,
0x3f803f80,0xbf803f80,0x3f803f80,0xbf803f80,0x3f803f80,0xbf803f80,0x3f803f80,0xbf803f80,0x3f803f80,0xbf803f80,0x3f803f80,0xbf803f80,
0x3f803f80,0xbf803f80,0x3f803f80,0xbf803f80,0xbe16bd49,0xbf7dbf80,0xbf4ebf3e,0xbf18bf2c,0xbeacbe79,0xbf71bf78,0xbf67bf5c,0xbedbbf04,
0xbf04bedb,0xbf5cbf67,0xbf78bf71,0xbe79beac,0xbf2cbf18,0xbf3ebf4e,0xbf80bf7d,0xbd49be16,0xbf75bf7f,0x3e953dc9,0x3e953dc9,0x3f753f7f,
0xbf46bf62,0x3f223ef1,0x3f223ef1,0x3f463f62,0xbef1bf22,0x3f623f46,0x3f623f46,0x3ef13f22,0xbdc9be95,0x3f7f3f75,0x3f7f3f75,0x3dc93e95,
0x3edb3e16,0x3f673f7d,0x3eac3f18,0xbf71bf4e,0x3f5c3f2c,0x3f043f3e,0xbe793d49,0xbf78bf80,0x3f803f78,0xbd493e79,0xbf3ebf04,0xbf2cbf5c,
0x3f4e3f71,0xbf18beac,0xbf7dbf67,0xbe16bedb,0x3f553f7b,0xbf0ebe48,0xbf55bf7b,0x3f0e3e48,0x3e483f0e,0xbf7bbf55,0xbe48bf0e,0x3f7b3f55,
0xbf0ebe48,0xbf55bf7b,0x3f0e3e48,0x3f553f7b,0xbf7bbf55,0xbe48bf0e,0x3f7b3f55,0x3e483f0e,0xbf2cbe79,0xbf3ebf78,0x3f803f5c,0x3d493f04,
0xbf7dbf71,0x3e16beac,0x3f183f67,0xbf4ebedb,0xbedbbf4e,0x3f673f18,0xbeac3e16,0xbf71bf7d,0x3f043d49,0x3f5c3f80,0xbf78bf3e,0xbe79bf2c,
0xbf22bf75,0x3f463e95,0xbf46be95,0xbf22bf75,0x3ef1bdc9,0x3f623f7f,0xbf62bf7f,0x3ef1bdc9,0x3f7f3f62,0xbdc93ef1,0x3dc9bef1,0x3f7f3f62,
0x3e953f46,0xbf75bf22,0x3f753f22,0x3e953f46,0x3f5c3eac,0x3f043f71,0x3e79bedb,0x3f783f67,0x3f2c3f7d,0xbf3ebe16,0x3f803f4e,0xbd493f18,
0xbf183d49,0xbf4ebf80,0x3e163f3e,0xbf7dbf2c,0xbf67bf78,0x3edbbe79,0xbf71bf04,0xbeacbf5c,0x3ec43f6d,0xbf6dbec4,0x3ec43f6d,0xbf6dbec4,
0xbf6dbec4,0xbec4bf6d,0xbf6dbec4,0xbec4bf6d,0xbec4bf6d,0x3f6d3ec4,0xbec4bf6d,0x3f6d3ec4,0x3f6d3ec4,0x3ec43f6d,0x3f6d3ec4,0x3ec43f6d,
0xbf78bedb,0xbe79bf67,0xbf5cbf71,0x3f04beac,0xbd49bf4e,0x3f803f18,0x3f2cbe16,0x3f3e3f7d,0x3f7d3f3e,0xbe163f2c,0x3f183f80,0xbf4ebd49,
0xbeac3f04,0xbf71bf5c,0xbf67be79,0xbedbbf78,0xbdc9bf62,0x3f7f3ef1,0x3f7f3ef1,0x3dc93f62,0x3f753f46,0xbe953f22,0xbe953f22,0xbf75bf46,
0xbf223e95,0xbf46bf75,0xbf46bf75,0x3f22be95,0xbef1bf7f,0x3f623dc9,0x3f623dc9,0x3ef13f7f,0x3f803f04,0xbd493f5c,0xbf3e3e79,0xbf2cbf78,
0xbf183edb,0xbf4ebf67,0xbe16bf71,0x3f7d3eac,0xbeacbf7d,0x3f713e16,0x3f673f4e,0xbedb3f18,0x3f783f2c,0xbe793f3e,0xbf5c3d49,0xbf04bf80,
0xbe483f55,0xbf7bbf0e,0x3e48bf55,0x3f7b3f0e,0xbf0ebf7b,0x3f55be48,0x3f0e3f7b,0xbf553e48,0x3f7b3f0e,0xbe483f55,0xbf7bbf0e,0x3e48bf55,
0xbf553e48,0xbf0ebf7b,0x3f55be48,0x3f0e3f7b,0xbf71bf18,0x3eacbf4e,0x3edb3f7d,0xbf673e16,0x3f783d49,0x3e793f80,0xbf5cbf3e,0x3f04bf2c,
0xbf2c3f04,0xbf3ebf5c,0x3f803e79,0x3d493f78,0x3e16bf67,0x3f7d3edb,0xbf4e3eac,0xbf18bf71,0x3ef1bf46,0x3f623f22,0xbf62bf22,0x3ef1bf46,
0xbdc93f75,0xbf7fbe95,0x3f7f3e95,0xbdc93f75,0xbe95bf7f,0x3f75bdc9,0xbf753dc9,0xbe95bf7f,0x3f223f62,0xbf463ef1,0x3f46bef1,0x3f223f62,
0x3f4e3f2c,0xbf183f3e,0x3f7dbd49,0x3e163f80,0xbf67bf04,0x3edbbf5c,0xbf713e79,0xbeacbf78,0x3f783eac,0xbe793f71,0x3f5cbedb,0x3f043f67,
0xbf80be16,0x3d49bf7d,0xbf3e3f18,0xbf2cbf4e,0xbf353f35,0xbf35bf35,0xbf353f35,0xbf35bf35,0x3f35bf35,0x3f353f35,0x3f35bf35,0x3f353f35,
0xbf353f35,0xbf35bf35,0xbf353f35,0xbf35bf35,0x3f35bf35,0x3f353f35,0x3f35bf35,0x3f353f35,0xbf18bf3e,0x3f4ebf2c,0x3e16bf80,0x3f7d3d49,
0x3edb3f5c,0xbf673f04,0xbeac3f78,0xbf71be79,0xbe79bf71,0x3f78beac,0x3f04bf67,0x3f5c3edb,0x3d493f7d,0xbf803e16,0xbf2c3f4e,0xbf3ebf18,
0x3f62bf22,0x3ef13f46,0x3ef13f46,0xbf623f22,0xbf7f3e95,0xbdc9bf75,0xbdc9bf75,0x3f7fbe95,0x3f753dc9,0xbe953f7f,0xbe953f7f,0xbf75bdc9,
0xbf46bef1,0x3f22bf62,0x3f22bf62,0x3f463ef1,0x3eac3f4e,0xbf713f18,0xbf67be16,0x3edbbf7d,0x3e79bf80,0x3f78bd49,0x3f043f2c,0xbf5c3f3e,
0xbf3e3f5c,0xbf2cbf04,0x3d49bf78,0x3f80be79,0x3f7dbedb,0x3e163f67,0xbf183f71,0xbf4ebeac,0xbf7b3f0e,0xbe48bf55,0x3f7bbf0e,0x3e483f55,
0x3f553e48,0xbf0e3f7b,0xbf55be48,0x3f0ebf7b,0xbe48bf55,0x3f7bbf0e,0x3e483f55,0xbf7b3f0e,0xbf0e3f7b,0xbf55be48,0x3f0ebf7b,0x3f553e48,
0xbd49bf5c,0x3f80bf04,0xbf2c3f78,0xbf3ebe79,0xbf4e3f67,0xbf18bedb,0x3f7dbeac,0xbe163f71,0x3f71be16,0xbeac3f7d,0xbedbbf18,0x3f67bf4e,
0xbe79bf3e,0x3f78bf2c,0xbf043f80,0xbf5cbd49,0x3f7fbef1,0xbdc93f62,0x3dc9bf62,0x3f7fbef1,0xbe95bf22,0x3f75bf46,0xbf753f46,0xbe95bf22,
0xbf463f75,0xbf22be95,0x3f223e95,0xbf463f75,0x3f62bdc9,0xbef13f7f,0x3ef1bf7f,0x3f62bdc9,0xbe793f67,0xbf783edb,0x3f043eac,0xbf5c3f71,
0x3f80bf18,0xbd493f4e,0x3f3ebf7d,0x3f2c3e16,0xbe16bf2c,0x3f7dbf3e,0xbf4e3d49,0x3f18bf80,0xbf713f5c,0xbeacbf04,0xbedb3f78,0xbf673e79,
0xbf6d3ec4,0x3ec4bf6d,0xbf6d3ec4,0x3ec4bf6d,0xbec43f6d,0xbf6d3ec4,0xbec43f6d,0xbf6d3ec4,0x3f6dbec4,0xbec43f6d,0x3f6dbec4,0xbec43f6d,
0x3ec4bf6d,0x3f6dbec4,0x3ec4bf6d,0x3f6dbec4,0x3f04bf71,0x3f5cbeac,0x3f78bf67,0x3e793edb,0xbf3e3e16,0x3f2cbf7d,0xbd49bf18,0x3f80bf4e,
0xbf4e3f80,0xbf18bd49,0xbf7d3f2c,0x3e16bf3e,0x3edb3e79,0xbf673f78,0xbeac3f5c,0xbf713f04,0x3f46be95,0xbf223f75,0xbf223f75,0xbf463e95,
0x3f62bf7f,0x3ef13dc9,0x3ef13dc9,0xbf623f7f,0xbdc9bef1,0x3f7fbf62,0x3f7fbf62,0x3dc93ef1,0xbf753f22,0x3e95bf46,0x3e95bf46,0x3f75bf22,
0xbf3e3f78,0xbf2c3e79,0x3d49bf04,0x3f80bf5c,0x3e163eac,0xbf7d3f71,0xbf4e3edb,0x3f18bf67,0x3f67bf18,0xbedb3f4e,0xbf713f7d,0xbeacbe16,
0x3f5cbf80,0x3f04bd49,0xbe793f2c,0xbf783f3e,0xbf0e3e48,0x3f55bf7b,0x3f0ebe48,0xbf553f7b,0xbf7b3f55,0x3e48bf0e,0x3f7bbf55,0xbe483f0e,
0xbf553f7b,0xbf0e3e48,0x3f55bf7b,0x3f0ebe48,0xbe483f0e,0xbf7b3f55,0x3e48bf0e,0x3f7bbf55,0x3f67bf7d,0x3edbbe16,0xbf713f4e,0x3eacbf18,
0x3f04bf3e,0x3f5cbf2c,0xbf783f80,0xbe79bd49,0xbd49be79,0x3f80bf78,0xbf2c3f5c,0xbf3e3f04,0xbf183eac,0x3f4ebf71,0xbe163edb,0xbf7d3f67,
0x3e95bdc9,0xbf753f7f,0x3f75bf7f,0x3e95bdc9,0x3f22bef1,0xbf463f62,0x3f46bf62,0x3f22bef1,0x3f62bf46,0xbef13f22,0x3ef1bf22,0x3f62bf46,
0x3f7fbf75,0xbdc93e95,0x3dc9be95,0x3f7fbf75,0xbf7d3f80,0xbe163d49,0xbf183f2c,0xbf4e3f3e,0xbf713f78,0xbeac3e79,0xbedb3f04,0xbf673f5c,
0xbf5c3f67,0xbf043edb,0xbe793eac,0xbf783f71,0xbf3e3f4e,0xbf2c3f18,0xbd493e16,0xbf803f7d,0x3f803f80,0xbf803f80,0x3f803f80,0xbf803f80,
0x3f803f80,0xbf803f80,0x3f803f80,0xbf803f80,0x3f803f80,0xbf803f80,0x3f803f80,0xbf803f80,0x3f803f80,0xbf803f80,0x3f803f80,0xbf803f80,
0xbf7dbf80,0x3e163d49,0xbf18bf2c,0x3f4e3f3e,0xbf71bf78,0x3eac3e79,0xbedbbf04,0x3f673f5c,0xbf5cbf67,0x3f043edb,0xbe79beac,0x3f783f71,
0xbf3ebf4e,0x3f2c3f18,0xbd49be16,0x3f803f7d,0x3f753f7f,0xbe95bdc9,0xbe95bdc9,0xbf75bf7f,0x3f463f62,0xbf22bef1,0xbf22bef1,0xbf46bf62,
0x3ef13f22,0xbf62bf46,0xbf62bf46,0xbef1bf22,0x3dc93e95,0xbf7fbf75,0xbf7fbf75,0xbdc9be95,0xbf67bf7d,0x3edb3e16,0x3f713f4e,0x3eac3f18,
0xbf04bf3e,0x3f5c3f2c,0x3f783f80,0xbe793d49,0x3d49be79,0x3f803f78,0x3f2c3f5c,0xbf3ebf04,0x3f183eac,0x3f4e3f71,0x3e163edb,0xbf7dbf67,
0x3f553f7b,0xbf0ebe48,0xbf55bf7b,0x3f0e3e48,0x3e483f0e,0xbf7bbf55,0xbe48bf0e,0x3f7b3f55,0xbf0ebe48,0xbf55bf7b,0x3f0e3e48,0x3f553f7b,
0xbf7bbf55,0xbe48bf0e,0x3f7b3f55,0x3e483f0e,0xbf3ebf78,0x3f2c3e79,0x3d493f04,0xbf80bf5c,0x3e16beac,0x3f7d3f71,0xbf4ebedb,0xbf18bf67,
0x3f673f18,0x3edb3f4e,0xbf71bf7d,0x3eacbe16,0x3f5c3f80,0xbf04bd49,0xbe79bf2c,0x3f783f3e,0x3f223f75,0xbf46be95,0x3f463e95,0x3f223f75,
0xbef13dc9,0xbf62bf7f,0x3f623f7f,0xbef13dc9,0xbf7fbf62,0x3dc9bef1,0xbdc93ef1,0xbf7fbf62,0xbe95bf46,0x3f753f22,0xbf75bf22,0xbe95bf46,
0xbf04bf71,0x3f5c3eac,0xbf78bf67,0x3e79bedb,0x3f3e3e16,0x3f2c3f7d,0x3d49bf18,0x3f803f4e,0x3f4e3f80,0xbf183d49,0x3f7d3f2c,0x3e163f3e,
0xbedb3e79,0xbf67bf78,0x3eac3f5c,0xbf71bf04,0x3ec43f6d,0xbf6dbec4,0x3ec43f6d,0xbf6dbec4,0xbf6dbec4,0xbec4bf6d,0xbf6dbec4,0xbec4bf6d,
0xbec4bf6d,0x3f6d3ec4,0xbec4bf6d,0x3f6d3ec4,0x3f6d3ec4,0x3ec43f6d,0x3f6d3ec4,0x3ec43f6d,0xbe79bf67,0x3f783edb,0x3f04beac,0x3f5c3f71,
0x3f803f18,0x3d493f4e,0x3f3e3f7d,0xbf2c3e16,0xbe163f2c,0xbf7dbf3e,0xbf4ebd49,0xbf18bf80,0xbf71bf5c,0x3eacbf04,0xbedbbf78,0x3f673e79,
0x3dc93f62,0xbf7fbef1,0xbf7fbef1,0xbdc9bf62,0xbf75bf46,0x3e95bf22,0x3e95bf22,0x3f753f46,0x3f22be95,0x3f463f75,0x3f463f75,0xbf223e95,
0x3ef13f7f,0xbf62bdc9,0xbf62bdc9,0xbef1bf7f,0x3d49bf5c,0x3f803f04,0x3f2c3f78,0xbf3e3e79,0x3f4e3f67,0xbf183edb,0xbf7dbeac,0xbe16bf71,
0xbf71be16,0xbeacbf7d,0x3edbbf18,0x3f673f4e,0x3e79bf3e,0x3f783f2c,0x3f043f80,0xbf5c3d49,0xbe483f55,0xbf7bbf0e,0x3e48bf55,0x3f7b3f0e,
0xbf0ebf7b,0x3f55be48,0x3f0e3f7b,0xbf553e48,0x3f7b3f0e,0xbe483f55,0xbf7bbf0e,0x3e48bf55,0xbf553e48,0xbf0ebf7b,0x3f55be48,0x3f0e3f7b,
0x3eacbf4e,0x3f713f18,0xbf673e16,0xbedbbf7d,0x3e793f80,0xbf78bd49,0x3f04bf2c,0x3f5c3f3e,0xbf3ebf5c,0x3f2cbf04,0x3d493f78,0xbf80be79,
0x3f7d3edb,0xbe163f67,0xbf18bf71,0x3f4ebeac,0xbef13f46,0xbf62bf22,0x3f623f22,0xbef13f46,0x3dc9bf75,0x3f7f3e95,0xbf7fbe95,0x3dc9bf75,
0x3e953f7f,0xbf753dc9,0x3f75bdc9,0x3e953f7f,0xbf22bf62,0x3f46bef1,0xbf463ef1,0xbf22bf62,0x3f18bf3e,0x3f4e3f2c,0xbe16bf80,0x3f7dbd49,
0xbedb3f5c,0xbf67bf04,0x3eac3f78,0xbf713e79,0x3e79bf71,0x3f783eac,0xbf04bf67,0x3f5cbedb,0xbd493f7d,0xbf80be16,0x3f2c3f4e,0xbf3e3f18,
0xbf353f35,0xbf35bf35,0xbf353f35,0xbf35bf35,0x3f35bf35,0x3f353f35,0x3f35bf35,0x3f353f35,0xbf353f35,0xbf35bf35,0xbf353f35,0xbf35bf35,
0x3f35bf35,0x3f353f35,0x3f35bf35,0x3f353f35,0x3f4ebf2c,0x3f183f3e,0x3f7d3d49,0xbe163f80,0xbf673f04,0xbedbbf5c,0xbf71be79,0x3eacbf78,
0x3f78beac,0x3e793f71,0x3f5c3edb,0xbf043f67,0xbf803e16,0xbd49bf7d,0xbf3ebf18,0x3f2cbf4e,0xbf623f22,0xbef1bf46,0xbef1bf46,0x3f62bf22,
0x3f7fbe95,0x3dc93f75,0x3dc93f75,0xbf7f3e95,0xbf75bdc9,0x3e95bf7f,0x3e95bf7f,0x3f753dc9,0x3f463ef1,0xbf223f62,0xbf223f62,0xbf46bef1,
0x3f71bf18,0x3eac3f4e,0xbedb3f7d,0xbf67be16,0xbf783d49,0x3e79bf80,0x3f5cbf3e,0x3f043f2c,0x3f2c3f04,0xbf3e3f5c,0xbf803e79,0x3d49bf78,
0xbe16bf67,0x3f7dbedb,0x3f4e3eac,0xbf183f71,0xbf7b3f0e,0xbe48bf55,0x3f7bbf0e,0x3e483f55,0x3f553e48,0xbf0e3f7b,0xbf55be48,0x3f0ebf7b,
0xbe48bf55,0x3f7bbf0e,0x3e483f55,0xbf7b3f0e,0xbf0e3f7b,0xbf55be48,0x3f0ebf7b,0x3f553e48,0x3f80bf04,0x3d493f5c,0xbf3ebe79,0x3f2cbf78,
0xbf18bedb,0x3f4ebf67,0xbe163f71,0xbf7d3eac,0xbeac3f7d,0xbf713e16,0x3f67bf4e,0x3edb3f18,0x3f78bf2c,0x3e793f3e,0xbf5cbd49,0x3f04bf80,
0xbf7f3ef1,0x3dc9bf62,0xbdc93f62,0xbf7f3ef1,0x3e953f22,0xbf753f46,0x3f75bf46,0x3e953f22,0x3f46bf75,0x3f223e95,0xbf22be95,0x3f46bf75,
0xbf623dc9,0x3ef1bf7f,0xbef13f7f,0xbf623dc9,0x3f78bedb,0xbe793f67,0x3f5cbf71,0x3f043eac,0x3d49bf4e,0x3f80bf18,0xbf2cbe16,0x3f3ebf7d,
0xbf7d3f3e,0xbe16bf2c,0xbf183f80,0xbf4e3d49,0x3eac3f04,0xbf713f5c,0x3f67be79,0xbedb3f78,0xbf6d3ec4,0x3ec4bf6d,0xbf6d3ec4,0x3ec4bf6d,
0xbec43f6d,0xbf6d3ec4,0xbec43f6d,0xbf6d3ec4,0x3f6dbec4,0xbec43f6d,0x3f6dbec4,0xbec43f6d,0x3ec4bf6d,0x3f6dbec4,0x3ec4bf6d,0x3f6dbec4,
0x3f5cbeac,0xbf043f71,0x3e793edb,0xbf783f67,0x3f2cbf7d,0x3f3ebe16,0x3f80bf4e,0x3d493f18,0xbf18bd49,0x3f4ebf80,0x3e16bf3e,0x3f7dbf2c,
0xbf673f78,0xbedbbe79,0xbf713f04,0x3eacbf5c,0xbf463e95,0x3f22bf75,0x3f22bf75,0x3f46be95,0xbf623f7f,0xbef1bdc9,0xbef1bdc9,0x3f62bf7f,
0x3dc93ef1,0xbf7f3f62,0xbf7f3f62,0xbdc9bef1,0x3f75bf22,0xbe953f46,0xbe953f46,0xbf753f22,0x3f2cbe79,0xbf3e3f78,0xbf803f5c,0x3d49bf04,
0x3f7dbf71,0x3e163eac,0xbf183f67,0xbf4e3edb,0x3edbbf4e,0x3f67bf18,0x3eac3e16,0xbf713f7d,0xbf043d49,0x3f5cbf80,0x3f78bf3e,0xbe793f2c,
0xbf0e3e48,0x3f55bf7b,0x3f0ebe48,0xbf553f7b,0xbf7b3f55,0x3e48bf0e,0x3f7bbf55,0xbe483f0e,0xbf553f7b,0xbf0e3e48,0x3f55bf7b,0x3f0ebe48,
0xbe483f0e,0xbf7b3f55,0x3e48bf0e,0x3f7bbf55,0x3edbbe16,0xbf673f7d,0x3eacbf18,0x3f71bf4e,0x3f5cbf2c,0xbf043f3e,0xbe79bd49,0x3f78bf80,
0x3f80bf78,0x3d493e79,0xbf3e3f04,0x3f2cbf5c,0x3f4ebf71,0x3f18beac,0xbf7d3f67,0x3e16bedb,0xbe953dc9,0x3f75bf7f,0xbf753f7f,0xbe953dc9,
0xbf223ef1,0x3f46bf62,0xbf463f62,0xbf223ef1,0xbf623f46,0x3ef1bf22,0xbef13f22,0xbf623f46,0xbf7f3f75,0x3dc9be95,0xbdc93e95,0xbf7f3f75,
0x3e16bd49,0xbf7d3f80,0x3f4ebf3e,0xbf183f2c,0x3eacbe79,0xbf713f78,0x3f67bf5c,0xbedb3f04,0x3f04bedb,0xbf5c3f67,0x3f78bf71,0xbe793eac,
0x3f2cbf18,0xbf3e3f4e,0x3f80bf7d,0xbd493e16,0x3f803f80,0xbf803f80,0x3f803f80,0xbf803f80,0x3f803f80,0xbf803f80,0x3f803f80,0xbf803f80,
0x3f803f80,0xbf803f80,0x3f803f80,0xbf803f80,0x3f803f80,0xbf803f80,0x3f803f80,0xbf803f80,0x3e163d49,0x3f7d3f80,0x3f4e3f3e,0x3f183f2c,
0x3eac3e79,0x3f713f78,0x3f673f5c,0x3edb3f04,0x3f043edb,0x3f5c3f67,0x3f783f71,0x3e793eac,0x3f2c3f18,0x3f3e3f4e,0x3f803f7d,0x3d493e16,
0xbf75bf7f,0x3e953dc9,0x3e953dc9,0x3f753f7f,0xbf46bf62,0x3f223ef1,0x3f223ef1,0x3f463f62,0xbef1bf22,0x3f623f46,0x3f623f46,0x3ef13f22,
0xbdc9be95,0x3f7f3f75,0x3f7f3f75,0x3dc93e95,0xbedbbe16,0xbf67bf7d,0xbeacbf18,0x3f713f4e,0xbf5cbf2c,0xbf04bf3e,0x3e79bd49,0x3f783f80,
0xbf80bf78,0x3d49be79,0x3f3e3f04,0x3f2c3f5c,0xbf4ebf71,0x3f183eac,0x3f7d3f67,0x3e163edb,0x3f553f7b,0xbf0ebe48,0xbf55bf7b,0x3f0e3e48,
0x3e483f0e,0xbf7bbf55,0xbe48bf0e,0x3f7b3f55,0xbf0ebe48,0xbf55bf7b,0x3f0e3e48,0x3f553f7b,0xbf7bbf55,0xbe48bf0e,0x3f7b3f55,0x3e483f0e,
0x3f2c3e79,0x3f3e3f78,0xbf80bf5c,0xbd49bf04,0x3f7d3f71,0xbe163eac,0xbf18bf67,0x3f4e3edb,0x3edb3f4e,0xbf67bf18,0x3eacbe16,0x3f713f7d,
0xbf04bd49,0xbf5cbf80,0x3f783f3e,0x3e793f2c,0xbf22bf75,0x3f463e95,0xbf46be95,0xbf22bf75,0x3ef1bdc9,0x3f623f7f,0xbf62bf7f,0x3ef1bdc9,
0x3f7f3f62,0xbdc93ef1,0x3dc9bef1,0x3f7f3f62,0x3e953f46,0xbf75bf22,0x3f753f22,0x3e953f46,0xbf5cbeac,0xbf04bf71,0xbe793edb,0xbf78bf67,
0xbf2cbf7d,0x3f3e3e16,0xbf80bf4e,0x3d49bf18,0x3f18bd49,0x3f4e3f80,0xbe16bf3e,0x3f7d3f2c,0x3f673f78,0xbedb3e79,0x3f713f04,0x3eac3f5c,
0x3ec43f6d,0xbf6dbec4,0x3ec43f6d,0xbf6dbec4,0xbf6dbec4,0xbec4bf6d,0xbf6dbec4,0xbec4bf6d,0xbec4bf6d,0x3f6d3ec4,0xbec4bf6d,0x3f6d3ec4,
0x3f6d3ec4,0x3ec43f6d,0x3f6d3ec4,0x3ec43f6d,0x3f783edb,0x3e793f67,0x3f5c3f71,0xbf043eac,0x3d493f4e,0xbf80bf18,0xbf2c3e16,0xbf3ebf7d,
0xbf7dbf3e,0x3e16bf2c,0xbf18bf80,0x3f4e3d49,0x3eacbf04,0x3f713f5c,0x3f673e79,0x3edb3f78,0xbdc9bf62,0x3f7f3ef1,0x3f7f3ef1,0x3dc93f62,
0x3f753f46,0xbe953f22,0xbe953f22,0xbf75bf46,0xbf223e95,0xbf46bf75,0xbf46bf75,0x3f22be95,0xbef1bf7f,0x3f623dc9,0x3f623dc9,0x3ef13f7f,
0xbf80bf04,0x3d49bf5c,0x3f3ebe79,0x3f2c3f78,0x3f18bedb,0x3f4e3f67,0x3e163f71,0xbf7dbeac,0x3eac3f7d,0xbf71be16,0xbf67bf4e,0x3edbbf18,
0xbf78bf2c,0x3e79bf3e,0x3f5cbd49,0x3f043f80,0xbe483f55,0xbf7bbf0e,0x3e48bf55,0x3f7b3f0e,0xbf0ebf7b,0x3f55be48,0x3f0e3f7b,0xbf553e48,
0x3f7b3f0e,0xbe483f55,0xbf7bbf0e,0x3e48bf55,0xbf553e48,0xbf0ebf7b,0x3f55be48,0x3f0e3f7b,0x3f713f18,0xbeac3f4e,0xbedbbf7d,0x3f67be16,
0xbf78bd49,0xbe79bf80,0x3f5c3f3e,0xbf043f2c,0x3f2cbf04,0x3f3e3f5c,0xbf80be79,0xbd49bf78,0xbe163f67,0xbf7dbedb,0x3f4ebeac,0x3f183f71,
0x3ef1bf46,0x3f623f22,0xbf62bf22,0x3ef1bf46,0xbdc93f75,0xbf7fbe95,0x3f7f3e95,0xbdc93f75,0xbe95bf7f,0x3f75bdc9,0xbf753dc9,0xbe95bf7f,
0x3f223f62,0xbf463ef1,0x3f46bef1,0x3f223f62,0xbf4ebf2c,0x3f18bf3e,0xbf7d3d49,0xbe16bf80,0x3f673f04,0xbedb3f5c,0x3f71be79,0x3eac3f78,
0xbf78beac,0x3e79bf71,0xbf5c3edb,0xbf04bf67,0x3f803e16,0xbd493f7d,0x3f3ebf18,0x3f2c3f4e,0xbf353f35,0xbf35bf35,0xbf353f35,0xbf35bf35,
0x3f35bf35,0x3f353f35,0x3f35bf35,0x3f353f35,0xbf353f35,0xbf35bf35,0xbf353f35,0xbf35bf35,0x3f35bf35,0x3f353f35,0x3f35bf35,0x3f353f35,
0x3f183f3e,0xbf4e3f2c,0xbe163f80,0xbf7dbd49,0xbedbbf5c,0x3f67bf04,0x3eacbf78,0x3f713e79,0x3e793f71,0xbf783eac,0xbf043f67,0xbf5cbedb,
0xbd49bf7d,0x3f80be16,0x3f2cbf4e,0x3f3e3f18,0x3f62bf22,0x3ef13f46,0x3ef13f46,0xbf623f22,0xbf7f3e95,0xbdc9bf75,0xbdc9bf75,0x3f7fbe95,
0x3f753dc9,0xbe953f7f,0xbe953f7f,0xbf75bdc9,0xbf46bef1,0x3f22bf62,0x3f22bf62,0x3f463ef1,0xbeacbf4e,0x3f71bf18,0x3f673e16,0xbedb3f7d,
0xbe793f80,0xbf783d49,0xbf04bf2c,0x3f5cbf3e,0x3f3ebf5c,0x3f2c3f04,0xbd493f78,0xbf803e79,0xbf7d3edb,0xbe16bf67,0x3f18bf71,0x3f4e3eac,
0xbf7b3f0e,0xbe48bf55,0x3f7bbf0e,0x3e483f55,0x3f553e48,0xbf0e3f7b,0xbf55be48,0x3f0ebf7b,0xbe48bf55,0x3f7bbf0e,0x3e483f55,0xbf7b3f0e,
0xbf0e3f7b,0xbf55be48,0x3f0ebf7b,0x3f553e48,0x3d493f5c,0xbf803f04,0x3f2cbf78,0x3f3e3e79,0x3f4ebf67,0x3f183edb,0xbf7d3eac,0x3e16bf71,
0xbf713e16,0x3eacbf7d,0x3edb3f18,0xbf673f4e,0x3e793f3e,0xbf783f2c,0x3f04bf80,0x3f5c3d49,0x3f7fbef1,0xbdc93f62,0x3dc9bf62,0x3f7fbef1,
0xbe95bf22,0x3f75bf46,0xbf753f46,0xbe95bf22,0xbf463f75,0xbf22be95,0x3f223e95,0xbf463f75,0x3f62bdc9,0xbef13f7f,0x3ef1bf7f,0x3f62bdc9,
0x3e79bf67,0x3f78bedb,0xbf04beac,0x3f5cbf71,0xbf803f18,0x3d49bf4e,0xbf3e3f7d,0xbf2cbe16,0x3e163f2c,0xbf7d3f3e,0x3f4ebd49,0xbf183f80,
0x3f71bf5c,0x3eac3f04,0x3edbbf78,0x3f67be79,0xbf6d3ec4,0x3ec4bf6d,0xbf6d3ec4,0x3ec4bf6d,0xbec43f6d,0xbf6d3ec4,0xbec43f6d,0xbf6d3ec4,
0x3f6dbec4,0xbec43f6d,0x3f6dbec4,0xbec43f6d,0x3ec4bf6d,0x3f6dbec4,0x3ec4bf6d,0x3f6dbec4,0xbf043f71,0xbf5c3eac,0xbf783f67,0xbe79bedb,
0x3f3ebe16,0xbf2c3f7d,0x3d493f18,0xbf803f4e,0x3f4ebf80,0x3f183d49,0x3f7dbf2c,0xbe163f3e,0xbedbbe79,0x3f67bf78,0x3eacbf5c,0x3f71bf04,
0x3f46be95,0xbf223f75,0xbf223f75,0xbf463e95,0x3f62bf7f,0x3ef13dc9,0x3ef13dc9,0xbf623f7f,0xbdc9bef1,0x3f7fbf62,0x3f7fbf62,0x3dc93ef1,
0xbf753f22,0x3e95bf46,0x3e95bf46,0x3f75bf22,0x3f3ebf78,0x3f2cbe79,0xbd493f04,0xbf803f5c,0xbe16beac,0x3f7dbf71,0x3f4ebedb,0xbf183f67,
0xbf673f18,0x3edbbf4e,0x3f71bf7d,0x3eac3e16,0xbf5c3f80,0xbf043d49,0x3e79bf2c,0x3f78bf3e,0xbf0e3e48,0x3f55bf7b,0x3f0ebe48,0xbf553f7b,
0xbf7b3f55,0x3e48bf0e,0x3f7bbf55,0xbe483f0e,0xbf553f7b,0xbf0e3e48,0x3f55bf7b,0x3f0ebe48,0xbe483f0e,0xbf7b3f55,0x3e48bf0e,0x3f7bbf55,
0xbf673f7d,0xbedb3e16,0x3f71bf4e,0xbeac3f18,0xbf043f3e,0xbf5c3f2c,0x3f78bf80,0x3e793d49,0x3d493e79,0xbf803f78,0x3f2cbf5c,0x3f3ebf04,
0x3f18beac,0xbf4e3f71,0x3e16bedb,0x3f7dbf67,0x3e95bdc9,0xbf753f7f,0x3f75bf7f,0x3e95bdc9,0x3f22bef1,0xbf463f62,0x3f46bf62,0x3f22bef1,
0x3f62bf46,0xbef13f22,0x3ef1bf22,0x3f62bf46,0x3f7fbf75,0xbdc93e95,0x3dc9be95,0x3f7fbf75,0x3f7dbf80,0x3e16bd49,0x3f18bf2c,0x3f4ebf3e,
0x3f71bf78,0x3eacbe79,0x3edbbf04,0x3f67bf5c,0x3f5cbf67,0x3f04bedb,0x3e79beac,0x3f78bf71,0x3f3ebf4e,0x3f2cbf18,0x3d49be16,0x3f80bf7d,
0x3f803f80,0xbf353f35,0x3f803f80,0xbf353f35,0x3f803f80,0xbf353f35,0x3f803f80,0xbf353f35,0x3f803f80,0xbf353f35,0x3f803f80,0xbf353f35,
0x3f803f80,0xbf353f35,0x3f803f80,0xbf353f35,0x3f7c3f7f,0xbe2fbd97,0x3f133f27,0xbf51bf42,0x3f6f3f77,0xbeb8be89,0x3ecf3efc,0xbf6abf5f,
0x3f583f65,0xbf09bee6,0x3e603ea1,0xbf7abf73,0x3f393f4a,0xbf31bf1d,0x3cc93dfb,0xbf80bf7e,0x3f713f7d,0xbeacbe16,0xbeacbe16,0xbf71bf7d,
0x3f3e3f5c,0xbf2cbf04,0xbf2cbf04,0xbf3ebf5c,0x3edb3f18,0xbf67bf4e,0xbf67bf4e,0xbedbbf18,0x3d493e79,0xbf80bf78,0xbf80bf78,0xbd49be79,
0x3f5f3f7a,0xbefcbe60,0xbf77bf58,0xbe89bf09,0x3ee63f31,0xbf65bf39,0xbf73bf80,0x3ea13cc9,0xbdfb3e2f,0xbf7ebf7c,0xbf1dbf51,0x3f4a3f13,
0xbf27becf,0xbf42bf6a,0xbd97beb8,0x3f7f3f6f,0x3f463f75,0xbf22be95,0xbf46bf75,0x3f223e95,0x3dc93ef1,0xbf7fbf62,0xbdc9bef1,0x3f7f3f62,
0xbf22be95,0xbf46bf75,0x3f223e95,0x3f463f75,0xbf7fbf62,0xbdc9bef1,0x3f7f3f62,0x3dc93ef1,0x3f273f6f,0xbf42beb8,0x3d97becf,0x3f7f3f6a,
0xbe893e60,0xbf77bf7a,0x3f5f3f09,0x3efc3f58,0xbf73bf31,0xbea1bf39,0x3f653f80,0xbee63cc9,0xbf4abf7c,0x3f1d3e2f,0x3dfb3f13,0xbf7ebf51,
0x3f043f67,0xbf5cbedb,0x3f5c3edb,0x3f043f67,0xbf18bd49,0xbf4ebf80,0x3f4e3f80,0xbf18bd49,0xbf78bf71,0x3e79beac,0xbe793eac,0xbf78bf71,
0xbe16bf2c,0x3f7d3f3e,0xbf7dbf3e,0xbe16bf2c,0x3eb83f5f,0xbf6fbefc,0x3f6a3f77,0xbecf3e89,0xbf58bea1,0xbf09bf73,0xbe603ee6,0xbf7abf65,
0xbf31bf7e,0x3f393dfb,0xbf80bf4a,0x3cc9bf1d,0x3f13bd97,0x3f513f7f,0xbe2fbf42,0x3f7c3f27,0x3e483f55,0xbf7bbf0e,0x3e483f55,0xbf7bbf0e,
0xbf7bbf0e,0xbe48bf55,0xbf7bbf0e,0xbe48bf55,0xbe48bf55,0x3f7b3f0e,0xbe48bf55,0x3f7b3f0e,0x3f7b3f0e,0x3e483f55,0x3f7b3f0e,0x3e483f55,
0x3cc93f4a,0xbf80bf1d,0xbf313dfb,0xbf39bf7e,0xbf7cbf42,0x3e2fbf27,0xbf13bf7f,0x3f513d97,0x3eb8befc,0x3f6f3f5f,0x3f6a3e89,0x3ecf3f77,
0x3f583f73,0xbf093ea1,0x3e603f65,0xbf7abee6,0xbe163f3e,0xbf7dbf2c,0xbf7dbf2c,0x3e16bf3e,0xbf5cbf67,0x3f04bedb,0x3f04bedb,0x3f5c3f67,
0x3f4ebd49,0x3f183f80,0x3f183f80,0xbf4e3d49,0x3e793f71,0xbf78beac,0xbf78beac,0xbe79bf71,0xbea13f31,0xbf73bf39,0xbee6bf80,0x3f653cc9,
0xbf1dbf7c,0x3f4abe2f,0x3f7e3f13,0xbdfb3f51,0x3f7f3ecf,0x3d973f6a,0xbf273eb8,0xbf42bf6f,0xbefc3f09,0xbf5fbf58,0xbe89bf7a,0x3f773e60,
0xbef13f22,0xbf62bf46,0x3ef1bf22,0x3f623f46,0xbe95bf7f,0x3f753dc9,0x3e953f7f,0xbf75bdc9,0x3f623f46,0xbef13f22,0xbf62bf46,0x3ef1bf22,
0xbf75bdc9,0xbe95bf7f,0x3f753dc9,0x3e953f7f,0xbf1d3f13,0xbf4abf51,0x3f7e3e2f,0x3dfb3f7c,0x3d97bf6f,0x3f7f3eb8,0xbf423ecf,0xbf27bf6a,
0x3efc3f7a,0xbf5f3e60,0x3e89bf58,0x3f773f09,0xbf65bf31,0x3ee6bf39,0x3ea13f80,0xbf733cc9,0xbf3e3f04,0xbf2cbf5c,0x3f2c3f5c,0xbf3e3f04,
0x3edbbf4e,0x3f673f18,0xbf67bf18,0x3edbbf4e,0xbd493f78,0xbf80be79,0x3f803e79,0xbd493f78,0xbeacbf7d,0x3f71be16,0xbf713e16,0xbeacbf7d,
0xbf583ee6,0xbf09bf65,0xbe603f73,0xbf7abea1,0x3f39bf1d,0x3f313f4a,0x3cc9bf7e,0x3f803dfb,0xbf133f42,0xbf51bf27,0x3e2f3f7f,0xbf7c3d97,
0x3ecfbf5f,0x3f6a3efc,0xbeb8bf77,0x3f6fbe89,0xbf6d3ec4,0xbec4bf6d,0xbf6d3ec4,0xbec4bf6d,0x3f6dbec4,0x3ec43f6d,0x3f6dbec4,0x3ec43f6d,
0xbf6d3ec4,0xbec4bf6d,0xbf6d3ec4,0xbec4bf6d,0x3f6dbec4,0x3ec43f6d,0x3f6dbec4,0x3ec43f6d,0xbf7a3ea1,0xbe60bf73,0xbf58bee6,0x3f09bf65,
0x3f80bdfb,0x3cc93f7e,0x3f393f1d,0xbf313f4a,0xbf7cbd97,0x3e2fbf7f,0xbf13bf42,0x3f51bf27,0x3f6f3e89,0xbeb83f77,0x3ecf3f5f,0xbf6a3efc,
0xbf803e79,0xbd49bf78,0xbd49bf78,0x3f80be79,0x3f713e16,0xbeac3f7d,0xbeac3f7d,0xbf71be16,0xbf3ebf04,0x3f2cbf5c,0x3f2cbf5c,0x3f3e3f04,
0x3edb3f4e,0xbf673f18,0xbf673f18,0xbedbbf4e,0xbf7e3e2f,0x3dfbbf7c,0x3f4abf51,0x3f1d3f13,0x3f423ecf,0xbf273f6a,0xbf7f3eb8,0xbd97bf6f,
0xbe89bf58,0x3f77bf09,0x3f5f3e60,0xbefc3f7a,0xbea13f80,0xbf73bcc9,0xbee6bf39,0x3f65bf31,0xbf753dc9,0x3e95bf7f,0x3f75bdc9,0xbe953f7f,
0x3ef13f22,0xbf623f46,0xbef1bf22,0x3f62bf46,0x3e95bf7f,0x3f75bdc9,0xbe953f7f,0xbf753dc9,0xbf623f46,0xbef1bf22,0x3f62bf46,0x3ef13f22,
0xbf653cc9,0x3ee6bf80,0x3ea13f31,0xbf733f39,0x3dfb3f51,0xbf7e3f13,0x3f1dbf7c,0x3f4a3e2f,0x3f42bf6f,0x3f273eb8,0xbf7f3ecf,0x3d97bf6a,
0xbf773e60,0x3e89bf7a,0x3efc3f09,0xbf5f3f58,0xbf4ebd49,0x3f18bf80,0xbf183f80,0xbf4ebd49,0xbe793f71,0xbf783eac,0x3f78beac,0xbe793f71,
0x3f7dbf2c,0x3e163f3e,0xbe16bf3e,0x3f7dbf2c,0xbf04bedb,0x3f5cbf67,0xbf5c3f67,0xbf04bedb,0xbf31bdfb,0x3f39bf7e,0xbf803f1d,0x3cc9bf4a,
0xbf133f7f,0xbf513d97,0x3e2f3f27,0xbf7c3f42,0x3f6abe89,0xbecf3f77,0x3f6fbf5f,0x3eb83efc,0x3e60bf65,0x3f7abee6,0xbf09bea1,0x3f58bf73,
0xbf0ebe48,0x3f55bf7b,0xbf0ebe48,0x3f55bf7b,0xbf553f7b,0xbf0ebe48,0xbf553f7b,0xbf0ebe48,0x3f0e3e48,0xbf553f7b,0x3f0e3e48,0xbf553f7b,
0x3f55bf7b,0x3f0e3e48,0x3f55bf7b,0x3f0e3e48,0xbecfbe89,0x3f6abf77,0x3eb8bf5f,0x3f6fbefc,0xbf7a3f65,0xbe60bee6,0xbf583ea1,0x3f09bf73,
0x3cc93f1d,0xbf803f4a,0xbf313f7e,0xbf393dfb,0x3f7cbf27,0xbe2f3f42,0x3f133d97,0xbf513f7f,0xbe79beac,0x3f78bf71,0x3f78bf71,0x3e793eac,
0xbf7d3f3e,0x3e16bf2c,0x3e16bf2c,0x3f7dbf3e,0xbf043f67,0xbf5c3edb,0xbf5c3edb,0x3f04bf67,0x3f18bd49,0xbf4e3f80,0xbf4e3f80,0xbf183d49,
0xbd97becf,0x3f7fbf6a,0x3f42beb8,0xbf273f6f,0xbf5f3f09,0x3efcbf58,0x3f77bf7a,0x3e893e60,0xbf653f80,0xbee6bcc9,0x3ea1bf39,0x3f73bf31,
0xbdfb3f13,0xbf7e3f51,0xbf1d3e2f,0x3f4abf7c,0x3dc9bef1,0x3f7fbf62,0xbdc93ef1,0xbf7f3f62,0xbf223e95,0x3f46bf75,0x3f22be95,0xbf463f75,
0xbf7f3f62,0x3dc9bef1,0x3f7fbf62,0xbdc93ef1,0xbf463f75,0xbf223e95,0x3f46bf75,0x3f22be95,0x3e89bf09,0x3f77bf58,0xbf5f3f7a,0xbefc3e60,
0xbea13cc9,0x3f73bf80,0xbee63f31,0xbf653f39,0xbf4a3f13,0x3f1dbf51,0x3dfb3e2f,0xbf7e3f7c,0xbf7f3f6f,0x3d97beb8,0x3f27becf,0xbf423f6a,
0x3edbbf18,0x3f67bf4e,0xbf673f4e,0x3edbbf18,0x3d49be79,0x3f80bf78,0xbf803f78,0x3d49be79,0xbeac3e16,0x3f71bf7d,0xbf713f7d,0xbeac3e16,
0xbf2c3f04,0x3f3ebf5c,0xbf3e3f5c,0xbf2c3f04,0x3f13bf27,0x3f51bf42,0xbe2f3d97,0x3f7cbf7f,0x3ecfbefc,0x3f6abf5f,0xbeb83e89,0x3f6fbf77,
0x3e60bea1,0x3f7abf73,0xbf093ee6,0x3f58bf65,0x3cc9bdfb,0x3f80bf7e,0xbf313f1d,0x3f39bf4a,0x3f803f80,0xbf353f35,0x3f803f80,0xbf353f35,
0x3f803f80,0xbf353f35,0x3f803f80,0xbf353f35,0x3f803f80,0xbf353f35,0x3f803f80,0xbf353f35,0x3f803f80,0xbf353f35,0x3f803f80,0xbf353f35,
0xbe2fbd97,0xbf7cbf7f,0xbf51bf42,0xbf13bf27,0xbeb8be89,0xbf6fbf77,0xbf6abf5f,0xbecfbefc,0xbf09bee6,0xbf58bf65,0xbf7abf73,0xbe60bea1,
0xbf31bf1d,0xbf39bf4a,0xbf80bf7e,0xbcc9bdfb,0xbf71bf7d,0x3eac3e16,0x3eac3e16,0x3f713f7d,0xbf3ebf5c,0x3f2c3f04,0x3f2c3f04,0x3f3e3f5c,
0xbedbbf18,0x3f673f4e,0x3f673f4e,0x3edb3f18,0xbd49be79,0x3f803f78,0x3f803f78,0x3d493e79,0x3efc3e60,0x3f5f3f7a,0x3e893f09,0xbf77bf58,
0x3f653f39,0x3ee63f31,0xbea1bcc9,0xbf73bf80,0x3f7e3f7c,0xbdfb3e2f,0xbf4abf13,0xbf1dbf51,0x3f423f6a,0xbf27becf,0xbf7fbf6f,0xbd97beb8,
0x3f463f75,0xbf22be95,0xbf46bf75,0x3f223e95,0x3dc93ef1,0xbf7fbf62,0xbdc9bef1,0x3f7f3f62,0xbf22be95,0xbf46bf75,0x3f223e95,0x3f463f75,
0xbf7fbf62,0xbdc9bef1,0x3f7f3f62,0x3dc93ef1,0xbf42beb8,0xbf27bf6f,0x3f7f3f6a,0xbd973ecf,0xbf77bf7a,0x3e89be60,0x3efc3f58,0xbf5fbf09,
0xbea1bf39,0x3f733f31,0xbee63cc9,0xbf65bf80,0x3f1d3e2f,0x3f4a3f7c,0xbf7ebf51,0xbdfbbf13,0xbf04bf67,0x3f5c3edb,0xbf5cbedb,0xbf04bf67,
0x3f183d49,0x3f4e3f80,0xbf4ebf80,0x3f183d49,0x3f783f71,0xbe793eac,0x3e79beac,0x3f783f71,0x3e163f2c,0xbf7dbf3e,0x3f7d3f3e,0x3e163f2c,
0x3f6f3efc,0x3eb83f5f,0x3ecfbe89,0x3f6a3f77,0x3f093f73,0xbf58bea1,0x3f7a3f65,0xbe603ee6,0xbf39bdfb,0xbf31bf7e,0xbcc93f1d,0xbf80bf4a,
0xbf51bf7f,0x3f13bd97,0xbf7cbf27,0xbe2fbf42,0x3e483f55,0xbf7bbf0e,0x3e483f55,0xbf7bbf0e,0xbf7bbf0e,0xbe48bf55,0xbf7bbf0e,0xbe48bf55,
0xbe48bf55,0x3f7b3f0e,0xbe48bf55,0x3f7b3f0e,0x3f7b3f0e,0x3e483f55,0x3f7b3f0e,0x3e483f55,0xbf80bf1d,0xbcc9bf4a,0xbf39bf7e,0x3f31bdfb,
0x3e2fbf27,0x3f7c3f42,0x3f513d97,0x3f133f7f,0x3f6f3f5f,0xbeb83efc,0x3ecf3f77,0xbf6abe89,0xbf093ea1,0xbf58bf73,0xbf7abee6,0xbe60bf65,
0x3e16bf3e,0x3f7d3f2c,0x3f7d3f2c,0xbe163f3e,0x3f5c3f67,0xbf043edb,0xbf043edb,0xbf5cbf67,0xbf4e3d49,0xbf18bf80,0xbf18bf80,0x3f4ebd49,
0xbe79bf71,0x3f783eac,0x3f783eac,0x3e793f71,0x3f733f39,0xbea13f31,0xbf65bcc9,0xbee6bf80,0xbf4a3e2f,0xbf1dbf7c,0x3dfbbf51,0x3f7e3f13,
0xbd97bf6a,0x3f7f3ecf,0x3f423f6f,0xbf273eb8,0x3f5f3f58,0xbefc3f09,0xbf77be60,0xbe89bf7a,0xbef13f22,0xbf62bf46,0x3ef1bf22,0x3f623f46,
0xbe95bf7f,0x3f753dc9,0x3e953f7f,0xbf75bdc9,0x3f623f46,0xbef13f22,0xbf62bf46,0x3ef1bf22,0xbf75bdc9,0xbe95bf7f,0x3f753dc9,0x3e953f7f,
0xbf4abf51,0x3f1dbf13,0x3dfb3f7c,0xbf7ebe2f,0x3f7f3eb8,0xbd973f6f,0xbf27bf6a,0x3f42becf,0xbf5f3e60,0xbefcbf7a,0x3f773f09,0xbe893f58,
0x3ee6bf39,0x3f653f31,0xbf733cc9,0xbea1bf80,0x3f3ebf04,0x3f2c3f5c,0xbf2cbf5c,0x3f3ebf04,0xbedb3f4e,0xbf67bf18,0x3f673f18,0xbedb3f4e,
0x3d49bf78,0x3f803e79,0xbf80be79,0x3d49bf78,0x3eac3f7d,0xbf713e16,0x3f71be16,0x3eac3f7d,0x3f093f65,0xbf583ee6,0x3f7a3ea1,0xbe603f73,
0xbf31bf4a,0x3f39bf1d,0xbf80bdfb,0x3cc9bf7e,0x3f513f27,0xbf133f42,0x3f7cbd97,0x3e2f3f7f,0xbf6abefc,0x3ecfbf5f,0xbf6f3e89,0xbeb8bf77,
0xbf6d3ec4,0xbec4bf6d,0xbf6d3ec4,0xbec4bf6d,0x3f6dbec4,0x3ec43f6d,0x3f6dbec4,0x3ec43f6d,0xbf6d3ec4,0xbec4bf6d,0xbf6d3ec4,0xbec4bf6d,
0x3f6dbec4,0x3ec43f6d,0x3f6dbec4,0x3ec43f6d,0xbe60bf73,0x3f7abea1,0x3f09bf65,0x3f583ee6,0x3cc93f7e,0xbf803dfb,0xbf313f4a,0xbf39bf1d,
0x3e2fbf7f,0x3f7c3d97,0x3f51bf27,0x3f133f42,0xbeb83f77,0xbf6fbe89,0xbf6a3efc,0xbecfbf5f,0x3f80be79,0x3d493f78,0x3d493f78,0xbf803e79,
0xbf71be16,0x3eacbf7d,0x3eacbf7d,0x3f713e16,0x3f3e3f04,0xbf2c3f5c,0xbf2c3f5c,0xbf3ebf04,0xbedbbf4e,0x3f67bf18,0x3f67bf18,0x3edb3f4e,
0xbdfb3f7c,0xbf7e3e2f,0xbf1dbf13,0x3f4abf51,0x3f27bf6a,0x3f423ecf,0x3d973f6f,0xbf7f3eb8,0xbf773f09,0xbe89bf58,0x3efcbf7a,0x3f5f3e60,
0x3f733cc9,0xbea13f80,0xbf653f31,0xbee6bf39,0xbf753dc9,0x3e95bf7f,0x3f75bdc9,0xbe953f7f,0x3ef13f22,0xbf623f46,0xbef1bf22,0x3f62bf46,
0x3e95bf7f,0x3f75bdc9,0xbe953f7f,0xbf753dc9,0xbf623f46,0xbef1bf22,0x3f62bf46,0x3ef13f22,0x3ee6bf80,0x3f65bcc9,0xbf733f39,0xbea1bf31,
0xbf7e3f13,0xbdfbbf51,0x3f4a3e2f,0xbf1d3f7c,0x3f273eb8,0xbf423f6f,0x3d97bf6a,0x3f7fbecf,0x3e89bf7a,0x3f77be60,0xbf5f3f58,0xbefcbf09,
0x3f4e3d49,0xbf183f80,0x3f18bf80,0x3f4e3d49,0x3e79bf71,0x3f78beac,0xbf783eac,0x3e79bf71,0xbf7d3f2c,0xbe16bf3e,0x3e163f3e,0xbf7d3f2c,
0x3f043edb,0xbf5c3f67,0x3f5cbf67,0x3f043edb,0xbf393f7e,0xbf31bdfb,0xbcc93f4a,0xbf803f1d,0x3f51bd97,0xbf133f7f,0x3f7cbf42,0x3e2f3f27,
0x3ecfbf77,0x3f6abe89,0xbeb8befc,0x3f6fbf5f,0xbf7a3ee6,0x3e60bf65,0xbf583f73,0xbf09bea1,0xbf0ebe48,0x3f55bf7b,0xbf0ebe48,0x3f55bf7b,
0xbf553f7b,0xbf0ebe48,0xbf553f7b,0xbf0ebe48,0x3f0e3e48,0xbf553f7b,0x3f0e3e48,0xbf553f7b,0x3f55bf7b,0x3f0e3e48,0x3f55bf7b,0x3f0e3e48,
0x3f6abf77,0x3ecf3e89,0x3f6fbefc,0xbeb83f5f,0xbe60bee6,0x3f7abf65,0x3f09bf73,0x3f58bea1,0xbf803f4a,0xbcc9bf1d,0xbf393dfb,0x3f31bf7e,
0xbe2f3f42,0xbf7c3f27,0xbf513f7f,0xbf13bd97,0x3e793eac,0xbf783f71,0xbf783f71,0xbe79beac,0x3f7dbf3e,0xbe163f2c,0xbe163f2c,0xbf7d3f3e,
0x3f04bf67,0x3f5cbedb,0x3f5cbedb,0xbf043f67,0xbf183d49,0x3f4ebf80,0x3f4ebf80,0x3f18bd49,0xbf7f3f6a,0xbd97becf,0x3f27bf6f,0x3f42beb8,
0xbefc3f58,0xbf5f3f09,0xbe89be60,0x3f77bf7a,0x3ee63cc9,0xbf653f80,0xbf733f31,0x3ea1bf39,0x3f7ebf51,0xbdfb3f13,0xbf4a3f7c,0xbf1d3e2f,
0x3dc9bef1,0x3f7fbf62,0xbdc93ef1,0xbf7f3f62,0xbf223e95,0x3f46bf75,0x3f22be95,0xbf463f75,0xbf7f3f62,0x3dc9bef1,0x3f7fbf62,0xbdc93ef1,
0xbf463f75,0xbf223e95,0x3f46bf75,0x3f22be95,0x3f77bf58,0xbe893f09,0xbefc3e60,0x3f5fbf7a,0x3f73bf80,0x3ea1bcc9,0xbf653f39,0x3ee6bf31,
0x3f1dbf51,0x3f4abf13,0xbf7e3f7c,0xbdfbbe2f,0x3d97beb8,0x3f7fbf6f,0xbf423f6a,0xbf273ecf,0xbedb3f18,0xbf673f4e,0x3f67bf4e,0xbedb3f18,
0xbd493e79,0xbf803f78,0x3f80bf78,0xbd493e79,0x3eacbe16,0xbf713f7d,0x3f71bf7d,0x3eacbe16,0x3f2cbf04,0xbf3e3f5c,0x3f3ebf5c,0x3f2cbf04,
0xbf513f42,0x3f13bf27,0xbf7c3f7f,0xbe2f3d97,0xbf6a3f5f,0x3ecfbefc,0xbf6f3f77,0xbeb83e89,0xbf7a3f73,0x3e60bea1,0xbf583f65,0xbf093ee6,
0xbf803f7e,0x3cc9bdfb,0xbf393f4a,0xbf313f1d,0x3f803f80,0xbf353f35,0x3f803f80,0xbf353f35,0x3f803f80,0xbf353f35,0x3f803f80,0xbf353f35,
0x3f803f80,0xbf353f35,0x3f803f80,0xbf353f35,0x3f803f80,0xbf353f35,0x3f803f80,0xbf353f35,0xbf7cbf7f,0x3e2f3d97,0xbf13bf27,0x3f513f42,
0xbf6fbf77,0x3eb83e89,0xbecfbefc,0x3f6a3f5f,0xbf58bf65,0x3f093ee6,0xbe60bea1,0x3f7a3f73,0xbf39bf4a,0x3f313f1d,0xbcc9bdfb,0x3f803f7e,
0x3f713f7d,0xbeacbe16,0xbeacbe16,0xbf71bf7d,0x3f3e3f5c,0xbf2cbf04,0xbf2cbf04,0xbf3ebf5c,0x3edb3f18,0xbf67bf4e,0xbf67bf4e,0xbedbbf18,
0x3d493e79,0xbf80bf78,0xbf80bf78,0xbd49be79,0xbf5fbf7a,0x3efc3e60,0x3f773f58,0x3e893f09,0xbee6bf31,0x3f653f39,0x3f733f80,0xbea1bcc9,
0x3dfbbe2f,0x3f7e3f7c,0x3f1d3f51,0xbf4abf13,0x3f273ecf,0x3f423f6a,0x3d973eb8,0xbf7fbf6f,0x3f463f75,0xbf22be95,0xbf46bf75,0x3f223e95,
0x3dc93ef1,0xbf7fbf62,0xbdc9bef1,0x3f7f3f62,0xbf22be95,0xbf46bf75,0x3f223e95,0x3f463f75,0xbf7fbf62,0xbdc9bef1,0x3f7f3f62,0x3dc93ef1,
0xbf27bf6f,0x3f423eb8,0xbd973ecf,0xbf7fbf6a,0x3e89be60,0x3f773f7a,0xbf5fbf09,0xbefcbf58,0x3f733f31,0x3ea13f39,0xbf65bf80,0x3ee6bcc9,
0x3f4a3f7c,0xbf1dbe2f,0xbdfbbf13,0x3f7e3f51,0x3f043f67,0xbf5cbedb,0x3f5c3edb,0x3f043f67,0xbf18bd49,0xbf4ebf80,0x3f4e3f80,0xbf18bd49,
0xbf78bf71,0x3e79beac,0xbe793eac,0xbf78bf71,0xbe16bf2c,0x3f7d3f3e,0xbf7dbf3e,0xbe16bf2c,0xbeb8bf5f,0x3f6f3efc,0xbf6abf77,0x3ecfbe89,
0x3f583ea1,0x3f093f73,0x3e60bee6,0x3f7a3f65,0x3f313f7e,0xbf39bdfb,0x3f803f4a,0xbcc93f1d,0xbf133d97,0xbf51bf7f,0x3e2f3f42,0xbf7cbf27,
0x3e483f55,0xbf7bbf0e,0x3e483f55,0xbf7bbf0e,0xbf7bbf0e,0xbe48bf55,0xbf7bbf0e,0xbe48bf55,0xbe48bf55,0x3f7b3f0e,0xbe48bf55,0x3f7b3f0e,
0x3f7b3f0e,0x3e483f55,0x3f7b3f0e,0x3e483f55,0xbcc9bf4a,0x3f803f1d,0x3f31bdfb,0x3f393f7e,0x3f7c3f42,0xbe2f3f27,0x3f133f7f,0xbf51bd97,
0xbeb83efc,0xbf6fbf5f,0xbf6abe89,0xbecfbf77,0xbf58bf73,0x3f09bea1,0xbe60bf65,0x3f7a3ee6,0xbe163f3e,0xbf7dbf2c,0xbf7dbf2c,0x3e16bf3e,
0xbf5cbf67,0x3f04bedb,0x3f04bedb,0x3f5c3f67,0x3f4ebd49,0x3f183f80,0x3f183f80,0xbf4e3d49,0x3e793f71,0xbf78beac,0xbf78beac,0xbe79bf71,
0x3ea1bf31,0x3f733f39,0x3ee63f80,0xbf65bcc9,0x3f1d3f7c,0xbf4a3e2f,0xbf7ebf13,0x3dfbbf51,0xbf7fbecf,0xbd97bf6a,0x3f27beb8,0x3f423f6f,
0x3efcbf09,0x3f5f3f58,0x3e893f7a,0xbf77be60,0xbef13f22,0xbf62bf46,0x3ef1bf22,0x3f623f46,0xbe95bf7f,0x3f753dc9,0x3e953f7f,0xbf75bdc9,
0x3f623f46,0xbef13f22,0xbf62bf46,0x3ef1bf22,0xbf75bdc9,0xbe95bf7f,0x3f753dc9,0x3e953f7f,0x3f1dbf13,0x3f4a3f51,0xbf7ebe2f,0xbdfbbf7c,
0xbd973f6f,0xbf7fbeb8,0x3f42becf,0x3f273f6a,0xbefcbf7a,0x3f5fbe60,0xbe893f58,0xbf77bf09,0x3f653f31,0xbee63f39,0xbea1bf80,0x3f73bcc9,
0xbf3e3f04,0xbf2cbf5c,0x3f2c3f5c,0xbf3e3f04,0x3edbbf4e,0x3f673f18,0xbf67bf18,0x3edbbf4e,0xbd493f78,0xbf80be79,0x3f803e79,0xbd493f78,
0xbeacbf7d,0x3f71be16,0xbf713e16,0xbeacbf7d,0x3f58bee6,0x3f093f65,0x3e60bf73,0x3f7a3ea1,0xbf393f1d,0xbf31bf4a,0xbcc93f7e,0xbf80bdfb,
0x3f13bf42,0x3f513f27,0xbe2fbf7f,0x3f7cbd97,0xbecf3f5f,0xbf6abefc,0x3eb83f77,0xbf6f3e89,0xbf6d3ec4,0xbec4bf6d,0xbf6d3ec4,0xbec4bf6d,
0x3f6dbec4,0x3ec43f6d,0x3f6dbec4,0x3ec43f6d,0xbf6d3ec4,0xbec4bf6d,0xbf6d3ec4,0xbec4bf6d,0x3f6dbec4,0x3ec43f6d,0x3f6dbec4,0x3ec43f6d,
0x3f7abea1,0x3e603f73,0x3f583ee6,0xbf093f65,0xbf803dfb,0xbcc9bf7e,0xbf39bf1d,0x3f31bf4a,0x3f7c3d97,0xbe2f3f7f,0x3f133f42,0xbf513f27,
0xbf6fbe89,0x3eb8bf77,0xbecfbf5f,0x3f6abefc,0xbf803e79,0xbd49bf78,0xbd49bf78,0x3f80be79,0x3f713e16,0xbeac3f7d,0xbeac3f7d,0xbf71be16,
0xbf3ebf04,0x3f2cbf5c,0x3f2cbf5c,0x3f3e3f04,0x3edb3f4e,0xbf673f18,0xbf673f18,0xbedbbf4e,0x3f7ebe2f,0xbdfb3f7c,0xbf4a3f51,0xbf1dbf13,
0xbf42becf,0x3f27bf6a,0x3f7fbeb8,0x3d973f6f,0x3e893f58,0xbf773f09,0xbf5fbe60,0x3efcbf7a,0x3ea1bf80,0x3f733cc9,0x3ee63f39,0xbf653f31,
0xbf753dc9,0x3e95bf7f,0x3f75bdc9,0xbe953f7f,0x3ef13f22,0xbf623f46,0xbef1bf22,0x3f62bf46,0x3e95bf7f,0x3f75bdc9,0xbe953f7f,0xbf753dc9,
0xbf623f46,0xbef1bf22,0x3f62bf46,0x3ef13f22,0x3f65bcc9,0xbee63f80,0xbea1bf31,0x3f73bf39,0xbdfbbf51,0x3f7ebf13,0xbf1d3f7c,0xbf4abe2f,
0xbf423f6f,0xbf27beb8,0x3f7fbecf,0xbd973f6a,0x3f77be60,0xbe893f7a,0xbefcbf09,0x3f5fbf58,0xbf4ebd49,0x3f18bf80,0xbf183f80,0xbf4ebd49,
0xbe793f71,0xbf783eac,0x3f78beac,0xbe793f71,0x3f7dbf2c,0x3e163f3e,0xbe16bf3e,0x3f7dbf2c,0xbf04bedb,0x3f5cbf67,0xbf5c3f67,0xbf04bedb,
0x3f313dfb,0xbf393f7e,0x3f80bf1d,0xbcc93f4a,0x3f13bf7f,0x3f51bd97,0xbe2fbf27,0x3f7cbf42,0xbf6a3e89,0x3ecfbf77,0xbf6f3f5f,0xbeb8befc,
0xbe603f65,0xbf7a3ee6,0x3f093ea1,0xbf583f73,0xbf0ebe48,0x3f55bf7b,0xbf0ebe48,0x3f55bf7b,0xbf553f7b,0xbf0ebe48,0xbf553f7b,0xbf0ebe48,
0x3f0e3e48,0xbf553f7b,0x3f0e3e48,0xbf553f7b,0x3f55bf7b,0x3f0e3e48,0x3f55bf7b,0x3f0e3e48,0x3ecf3e89,0xbf6a3f77,0xbeb83f5f,0xbf6f3efc,
0x3f7abf65,0x3e603ee6,0x3f58bea1,0xbf093f73,0xbcc9bf1d,0x3f80bf4a,0x3f31bf7e,0x3f39bdfb,0xbf7c3f27,0x3e2fbf42,0xbf13bd97,0x3f51bf7f,
0xbe79beac,0x3f78bf71,0x3f78bf71,0x3e793eac,0xbf7d3f3e,0x3e16bf2c,0x3e16bf2c,0x3f7dbf3e,0xbf043f67,0xbf5c3edb,0xbf5c3edb,0x3f04bf67,
0x3f18bd49,0xbf4e3f80,0xbf4e3f80,0xbf183d49,0x3d973ecf,0xbf7f3f6a,0xbf423eb8,0x3f27bf6f,0x3f5fbf09,0xbefc3f58,0xbf773f7a,0xbe89be60,
0x3f65bf80,0x3ee63cc9,0xbea13f39,0xbf733f31,0x3dfbbf13,0x3f7ebf51,0x3f1dbe2f,0xbf4a3f7c,0x3dc9bef1,0x3f7fbf62,0xbdc93ef1,0xbf7f3f62,
0xbf223e95,0x3f46bf75,0x3f22be95,0xbf463f75,0xbf7f3f62,0x3dc9bef1,0x3f7fbf62,0xbdc93ef1,0xbf463f75,0xbf223e95,0x3f46bf75,0x3f22be95,
0xbe893f09,0xbf773f58,0x3f5fbf7a,0x3efcbe60,0x3ea1bcc9,0xbf733f80,0x3ee6bf31,0x3f65bf39,0x3f4abf13,0xbf1d3f51,0xbdfbbe2f,0x3f7ebf7c,
0x3f7fbf6f,0xbd973eb8,0xbf273ecf,0x3f42bf6a,0x3edbbf18,0x3f67bf4e,0xbf673f4e,0x3edbbf18,0x3d49be79,0x3f80bf78,0xbf803f78,0x3d49be79,
0xbeac3e16,0x3f71bf7d,0xbf713f7d,0xbeac3e16,0xbf2c3f04,0x3f3ebf5c,0xbf3e3f5c,0xbf2c3f04,0xbf133f27,0xbf513f42,0x3e2fbd97,0xbf7c3f7f,
0xbecf3efc,0xbf6a3f5f,0x3eb8be89,0xbf6f3f77,0xbe603ea1,0xbf7a3f73,0x3f09bee6,0xbf583f65,0xbcc93dfb,0xbf803f7e,0x3f31bf1d,0xbf393f4a,
0x3f803f80,0xbf353f35,0x3f803f80,0xbf353f35,0x3f803f80,0xbf353f35,0x3f803f80,0xbf353f35,0x3f803f80,0xbf353f35,0x3f803f80,0xbf353f35,
0x3f803f80,0xbf353f35,0x3f803f80,0xbf353f35,0x3e2f3d97,0x3f7c3f7f,0x3f513f42,0x3f133f27,0x3eb83e89,0x3f6f3f77,0x3f6a3f5f,0x3ecf3efc,
0x3f093ee6,0x3f583f65,0x3f7a3f73,0x3e603ea1,0x3f313f1d,0x3f393f4a,0x3f803f7e,0x3cc93dfb,0xbf71bf7d,0x3eac3e16,0x3eac3e16,0x3f713f7d,
0xbf3ebf5c,0x3f2c3f04,0x3f2c3f04,0x3f3e3f5c,0xbedbbf18,0x3f673f4e,0x3f673f4e,0x3edb3f18,0xbd49be79,0x3f803f78,0x3f803f78,0x3d493e79,
0xbefcbe60,0xbf5fbf7a,0xbe89bf09,0x3f773f58,0xbf65bf39,0xbee6bf31,0x3ea13cc9,0x3f733f80,0xbf7ebf7c,0x3dfbbe2f,0x3f4a3f13,0x3f1d3f51,
0xbf42bf6a,0x3f273ecf,0x3f7f3f6f,0x3d973eb8,0x3f463f75,0xbf22be95,0xbf46bf75,0x3f223e95,0x3dc93ef1,0xbf7fbf62,0xbdc9bef1,0x3f7f3f62,
0xbf22be95,0xbf46bf75,0x3f223e95,0x3f463f75,0xbf7fbf62,0xbdc9bef1,0x3f7f3f62,0x3dc93ef1,0x3f423eb8,0x3f273f6f,0xbf7fbf6a,0x3d97becf,
0x3f773f7a,0xbe893e60,0xbefcbf58,0x3f5f3f09,0x3ea13f39,0xbf73bf31,0x3ee6bcc9,0x3f653f80,0xbf1dbe2f,0xbf4abf7c,0x3f7e3f51,0x3dfb3f13,
0xbf04bf67,0x3f5c3edb,0xbf5cbedb,0xbf04bf67,0x3f183d49,0x3f4e3f80,0xbf4ebf80,0x3f183d49,0x3f783f71,0xbe793eac,0x3e79beac,0x3f783f71,
0x3e163f2c,0xbf7dbf3e,0x3f7d3f3e,0x3e163f2c,0xbf6fbefc,0xbeb8bf5f,0xbecf3e89,0xbf6abf77,0xbf09bf73,0x3f583ea1,0xbf7abf65,0x3e60bee6,
0x3f393dfb,0x3f313f7e,0x3cc9bf1d,0x3f803f4a,0x3f513f7f,0xbf133d97,0x3f7c3f27,0x3e2f3f42,0x3e483f55,0xbf7bbf0e,0x3e483f55,0xbf7bbf0e,
0xbf7bbf0e,0xbe48bf55,0xbf7bbf0e,0xbe48bf55,0xbe48bf55,0x3f7b3f0e,0xbe48bf55,0x3f7b3f0e,0x3f7b3f0e,0x3e483f55,0x3f7b3f0e,0x3e483f55,
0x3f803f1d,0x3cc93f4a,0x3f393f7e,0xbf313dfb,0xbe2f3f27,0xbf7cbf42,0xbf51bd97,0xbf13bf7f,0xbf6fbf5f,0x3eb8befc,0xbecfbf77,0x3f6a3e89,
0x3f09bea1,0x3f583f73,0x3f7a3ee6,0x3e603f65,0x3e16bf3e,0x3f7d3f2c,0x3f7d3f2c,0xbe163f3e,0x3f5c3f67,0xbf043edb,0xbf043edb,0xbf5cbf67,
0xbf4e3d49,0xbf18bf80,0xbf18bf80,0x3f4ebd49,0xbe79bf71,0x3f783eac,0x3f783eac,0x3e793f71,0xbf73bf39,0x3ea1bf31,0x3f653cc9,0x3ee63f80,
0x3f4abe2f,0x3f1d3f7c,0xbdfb3f51,0xbf7ebf13,0x3d973f6a,0xbf7fbecf,0xbf42bf6f,0x3f27beb8,0xbf5fbf58,0x3efcbf09,0x3f773e60,0x3e893f7a,
0xbef13f22,0xbf62bf46,0x3ef1bf22,0x3f623f46,0xbe95bf7f,0x3f753dc9,0x3e953f7f,0xbf75bdc9,0x3f623f46,0xbef13f22,0xbf62bf46,0x3ef1bf22,
0xbf75bdc9,0xbe95bf7f,0x3f753dc9,0x3e953f7f,0x3f4a3f51,0xbf1d3f13,0xbdfbbf7c,0x3f7e3e2f,0xbf7fbeb8,0x3d97bf6f,0x3f273f6a,0xbf423ecf,
0x3f5fbe60,0x3efc3f7a,0xbf77bf09,0x3e89bf58,0xbee63f39,0xbf65bf31,0x3f73bcc9,0x3ea13f80,0x3f3ebf04,0x3f2c3f5c,0xbf2cbf5c,0x3f3ebf04,
0xbedb3f4e,0xbf67bf18,0x3f673f18,0xbedb3f4e,0x3d49bf78,0x3f803e79,0xbf80be79,0x3d49bf78,0x3eac3f7d,0xbf713e16,0x3f71be16,0x3eac3f7d,
0xbf09bf65,0x3f58bee6,0xbf7abea1,0x3e60bf73,0x3f313f4a,0xbf393f1d,0x3f803dfb,0xbcc93f7e,0xbf51bf27,0x3f13bf42,0xbf7c3d97,0xbe2fbf7f,
0x3f6a3efc,0xbecf3f5f,0x3f6fbe89,0x3eb83f77,0xbf6d3ec4,0xbec4bf6d,0xbf6d3ec4,0xbec4bf6d,0x3f6dbec4,0x3ec43f6d,0x3f6dbec4,0x3ec43f6d,
0xbf6d3ec4,0xbec4bf6d,0xbf6d3ec4,0xbec4bf6d,0x3f6dbec4,0x3ec43f6d,0x3f6dbec4,0x3ec43f6d,0x3e603f73,0xbf7a3ea1,0xbf093f65,0xbf58bee6,
0xbcc9bf7e,0x3f80bdfb,0x3f31bf4a,0x3f393f1d,0xbe2f3f7f,0xbf7cbd97,0xbf513f27,0xbf13bf42,0x3eb8bf77,0x3f6f3e89,0x3f6abefc,0x3ecf3f5f,
0x3f80be79,0x3d493f78,0x3d493f78,0xbf803e79,0xbf71be16,0x3eacbf7d,0x3eacbf7d,0x3f713e16,0x3f3e3f04,0xbf2c3f5c,0xbf2c3f5c,0xbf3ebf04,
0xbedbbf4e,0x3f67bf18,0x3f67bf18,0x3edb3f4e,0x3dfbbf7c,0x3f7ebe2f,0x3f1d3f13,0xbf4a3f51,0xbf273f6a,0xbf42becf,0xbd97bf6f,0x3f7fbeb8,
0x3f77bf09,0x3e893f58,0xbefc3f7a,0xbf5fbe60,0xbf73bcc9,0x3ea1bf80,0x3f65bf31,0x3ee63f39,0xbf753dc9,0x3e95bf7f,0x3f75bdc9,0xbe953f7f,
0x3ef13f22,0xbf623f46,0xbef1bf22,0x3f62bf46,0x3e95bf7f,0x3f75bdc9,0xbe953f7f,0xbf753dc9,0xbf623f46,0xbef1bf22,0x3f62bf46,0x3ef13f22,
0xbee63f80,0xbf653cc9,0x3f73bf39,0x3ea13f31,0x3f7ebf13,0x3dfb3f51,0xbf4abe2f,0x3f1dbf7c,0xbf27beb8,0x3f42bf6f,0xbd973f6a,0xbf7f3ecf,
0xbe893f7a,0xbf773e60,0x3f5fbf58,0x3efc3f09,0x3f4e3d49,0xbf183f80,0x3f18bf80,0x3f4e3d49,0x3e79bf71,0x3f78beac,0xbf783eac,0x3e79bf71,
0xbf7d3f2c,0xbe16bf3e,0x3e163f3e,0xbf7d3f2c,0x3f043edb,0xbf5c3f67,0x3f5cbf67,0x3f043edb,0x3f39bf7e,0x3f313dfb,0x3cc9bf4a,0x3f80bf1d,
0xbf513d97,0x3f13bf7f,0xbf7c3f42,0xbe2fbf27,0xbecf3f77,0xbf6a3e89,0x3eb83efc,0xbf6f3f5f,0x3f7abee6,0xbe603f65,0x3f58bf73,0x3f093ea1,
0xbf0ebe48,0x3f55bf7b,0xbf0ebe48,0x3f55bf7b,0xbf553f7b,0xbf0ebe48,0xbf553f7b,0xbf0ebe48,0x3f0e3e48,0xbf553f7b,0x3f0e3e48,0xbf553f7b,
0x3f55bf7b,0x3f0e3e48,0x3f55bf7b,0x3f0e3e48,0xbf6a3f77,0xbecfbe89,0xbf6f3efc,0x3eb8bf5f,0x3e603ee6,0xbf7a3f65,0xbf093f73,0xbf583ea1,
0x3f80bf4a,0x3cc93f1d,0x3f39bdfb,0xbf313f7e,0x3e2fbf42,0x3f7cbf27,0x3f51bf7f,0x3f133d97,0x3e793eac,0xbf783f71,0xbf783f71,0xbe79beac,
0x3f7dbf3e,0xbe163f2c,0xbe163f2c,0xbf7d3f3e,0x3f04bf67,0x3f5cbedb,0x3f5cbedb,0xbf043f67,0xbf183d49,0x3f4ebf80,0x3f4ebf80,0x3f18bd49,
0x3f7fbf6a,0x3d973ecf,0xbf273f6f,0xbf423eb8,0x3efcbf58,0x3f5fbf09,0x3e893e60,0xbf773f7a,0xbee6bcc9,0x3f65bf80,0x3f73bf31,0xbea13f39,
0xbf7e3f51,0x3dfbbf13,0x3f4abf7c,0x3f1dbe2f,0x3dc9bef1,0x3f7fbf62,0xbdc93ef1,0xbf7f3f62,0xbf223e95,0x3f46bf75,0x3f22be95,0xbf463f75,
0xbf7f3f62,0x3dc9bef1,0x3f7fbf62,0xbdc93ef1,0xbf463f75,0xbf223e95,0x3f46bf75,0x3f22be95,0xbf773f58,0x3e89bf09,0x3efcbe60,0xbf5f3f7a,
0xbf733f80,0xbea13cc9,0x3f65bf39,0xbee63f31,0xbf1d3f51,0xbf4a3f13,0x3f7ebf7c,0x3dfb3e2f,0xbd973eb8,0xbf7f3f6f,0x3f42bf6a,0x3f27becf,
0xbedb3f18,0xbf673f4e,0x3f67bf4e,0xbedb3f18,0xbd493e79,0xbf803f78,0x3f80bf78,0xbd493e79,0x3eacbe16,0xbf713f7d,0x3f71bf7d,0x3eacbe16,
0x3f2cbf04,0xbf3e3f5c,0x3f3ebf5c,0x3f2cbf04,0x3f51bf42,0xbf133f27,0x3f7cbf7f,0x3e2fbd97,0x3f6abf5f,0xbecf3efc,0x3f6fbf77,0x3eb8be89,
0x3f7abf73,0xbe603ea1,0x3f58bf65,0x3f09bee6,0x3f80bf7e,0xbcc93dfb,0x3f39bf4a,0x3f31bf1d,0x3f803f80,0x3f803f80,0x3f803f80,0x3f803f80,
0x0,0x0,0x0,0x0,0x3f803f80,0x3f803f80,0x3f803f80,0x3f803f80,0x0,0x0,0x0,0x0,
0x3f803f80,0x3f803f80,0x3f803f80,0x3f803f80,0x0,0x0,0x0,0x0,0x3f803f80,0x3f803f80,0x3f803f80,0x3f803f80,
0x0,0x0,0x0,0x0,0x3e480000,0x3f0e3ec4,0x3f553f35,0x3f7b3f6d,0x3f7b3f80,0x3f553f6d,0x3f0e3f35,0x3e483ec4,
0x3f7b3f80,0x3f553f6d,0x3f0e3f35,0x3e483ec4,0xbe480000,0xbf0ebec4,0xbf55bf35,0xbf7bbf6d,0xbe480000,0xbf0ebec4,0xbf55bf35,0xbf7bbf6d,
0xbf7bbf80,0xbf55bf6d,0xbf0ebf35,0xbe48bec4,0xbf7bbf80,0xbf55bf6d,0xbf0ebf35,0xbe48bec4,0x3e480000,0x3f0e3ec4,0x3f553f35,0x3f7b3f6d,
0xbf6dbf80,0xbec4bf35,0x3ec40000,0x3f6d3f35,0xbec40000,0xbf6dbf35,0xbf6dbf80,0xbec4bf35,0x3f6d3f80,0x3ec43f35,0xbec40000,0xbf6dbf35,
0x3ec40000,0x3f6d3f35,0x3f6d3f80,0x3ec43f35,0xbf6dbf80,0xbec4bf35,0x3ec40000,0x3f6d3f35,0xbec40000,0xbf6dbf35,0xbf6dbf80,0xbec4bf35,
0x3f6d3f80,0x3ec43f35,0xbec40000,0xbf6dbf35,0x3ec40000,0x3f6d3f35,0x3f6d3f80,0x3ec43f35,0xbf55bf80,0x3e48bec4,0x3f7b3f35,0x3f0e3f6d,
0x3f0e0000,0x3f7b3f6d,0x3e483f35,0xbf55bec4,0x3f0e0000,0x3f7b3f6d,0x3e483f35,0xbf55bec4,0x3f553f80,0xbe483ec4,0xbf7bbf35,0xbf0ebf6d,
0x3f553f80,0xbe483ec4,0xbf7bbf35,0xbf0ebf6d,0xbf0e0000,0xbf7bbf6d,0xbe48bf35,0x3f553ec4,0xbf0e0000,0xbf7bbf6d,0xbe48bf35,0x3f553ec4,
0xbf55bf80,0x3e48bec4,0x3f7b3f35,0x3f0e3f6d,0x3f353f80,0xbf350000,0xbf35bf80,0x3f350000,0x3f350000,0x3f353f80,0xbf350000,0xbf35bf80,
0x3f353f80,0xbf350000,0xbf35bf80,0x3f350000,0x3f350000,0x3f353f80,0xbf350000,0xbf35bf80,0x3f353f80,0xbf350000,0xbf35bf80,0x3f350000,
0x3f350000,0x3f353f80,0xbf350000,0xbf35bf80,0x3f353f80,0xbf350000,0xbf35bf80,0x3f350000,0x3f350000,0x3f353f80,0xbf350000,0xbf35bf80,
0xbf550000,0xbe48bf6d,0x3f7b3f35,0xbf0e3ec4,0xbf0ebf80,0x3f7b3ec4,0xbe483f35,0xbf55bf6d,0xbf0ebf80,0x3f7b3ec4,0xbe483f35,0xbf55bf6d,
0x3f550000,0x3e483f6d,0xbf7bbf35,0x3f0ebec4,0x3f550000,0x3e483f6d,0xbf7bbf35,0x3f0ebec4,0x3f0e3f80,0xbf7bbec4,0x3e48bf35,0x3f553f6d,
0x3f0e3f80,0xbf7bbec4,0x3e48bf35,0x3f553f6d,0xbf550000,0xbe48bf6d,0x3f7b3f35,0xbf0e3ec4,0xbec4bf80,0x3f6d3f35,0xbf6d0000,0x3ec4bf35,
0xbf6d0000,0x3ec4bf35,0x3ec43f80,0xbf6dbf35,0x3ec43f80,0xbf6dbf35,0x3f6d0000,0xbec43f35,0x3f6d0000,0xbec43f35,0xbec4bf80,0x3f6d3f35,
0xbec4bf80,0x3f6d3f35,0xbf6d0000,0x3ec4bf35,0xbf6d0000,0x3ec4bf35,0x3ec43f80,0xbf6dbf35,0x3ec43f80,0xbf6dbf35,0x3f6d0000,0xbec43f35,
0x3f6d0000,0xbec43f35,0xbec4bf80,0x3f6d3f35,0x3e483f80,0xbf0ebf6d,0x3f553f35,0xbf7bbec4,0xbf7b0000,0x3f55bec4,0xbf0e3f35,0x3e48bf6d,
0xbf7b0000,0x3f55bec4,0xbf0e3f35,0x3e48bf6d,0xbe48bf80,0x3f0e3f6d,0xbf55bf35,0x3f7b3ec4,0xbe48bf80,0x3f0e3f6d,0xbf55bf35,0x3f7b3ec4,
0x3f7b0000,0xbf553ec4,0x3f0ebf35,0xbe483f6d,0x3f7b0000,0xbf553ec4,0x3f0ebf35,0xbe483f6d,0x3e483f80,0xbf0ebf6d,0x3f553f35,0xbf7bbec4,
0x80008000,0x80008000,0x80008000,0x80008000,0x3f803f80,0x3f803f80,0x3f803f80,0x3f803f80,0x80008000,0x80008000,0x80008000,0x80008000,
0x3f803f80,0x3f803f80,0x3f803f80,0x3f803f80,0x80008000,0x80008000,0x80008000,0x80008000,0x3f803f80,0x3f803f80,0x3f803f80,0x3f803f80,
0x80008000,0x80008000,0x80008000,0x80008000,0x3f803f80,0x3f803f80,0x3f803f80,0x3f803f80,0x3f7b3f80,0x3f553f6d,0x3f0e3f35,0x3e483ec4,
0xbe488000,0xbf0ebec4,0xbf55bf35,0xbf7bbf6d,0xbe480000,0xbf0ebec4,0xbf55bf35,0xbf7bbf6d,0xbf7bbf80,0xbf55bf6d,0xbf0ebf35,0xbe48bec4,
0xbf7bbf80,0xbf55bf6d,0xbf0ebf35,0xbe48bec4,0x3e488000,0x3f0e3ec4,0x3f553f35,0x3f7b3f6d,0x3e480000,0x3f0e3ec4,0x3f553f35,0x3f7b3f6d,
0x3f7b3f80,0x3f553f6d,0x3f0e3f35,0x3e483ec4,0x3ec48000,0x3f6d3f35,0x3f6d3f80,0x3ec43f35,0xbf6dbf80,0xbec4bf35,0x3ec40000,0x3f6d3f35,
0xbec48000,0xbf6dbf35,0xbf6dbf80,0xbec4bf35,0x3f6d3f80,0x3ec43f35,0xbec40000,0xbf6dbf35,0x3ec48000,0x3f6d3f35,0x3f6d3f80,0x3ec43f35,
0xbf6dbf80,0xbec4bf35,0x3ec40000,0x3f6d3f35,0xbec48000,0xbf6dbf35,0xbf6dbf80,0xbec4bf35,0x3f6d3f80,0x3ec43f35,0xbec40000,0xbf6dbf35,
0x3f0e0000,0x3f7b3f6d,0x3e483f35,0xbf55bec4,0x3f553f80,0xbe483ec4,0xbf7bbf35,0xbf0ebf6d,0x3f553f80,0xbe483ec4,0xbf7bbf35,0xbf0ebf6d,
0xbf0e8000,0xbf7bbf6d,0xbe48bf35,0x3f553ec4,0xbf0e0000,0xbf7bbf6d,0xbe48bf35,0x3f553ec4,0xbf55bf80,0x3e48bec4,0x3f7b3f35,0x3f0e3f6d,
0xbf55bf80,0x3e48bec4,0x3f7b3f35,0x3f0e3f6d,0x3f0e8000,0x3f7b3f6d,0x3e483f35,0xbf55bec4,0xbf358000,0xbf35bf80,0x3f358000,0x3f353f80,
0x3f353f80,0xbf350000,0xbf35bf80,0x3f350000,0xbf358000,0xbf35bf80,0x3f358000,0x3f353f80,0x3f353f80,0xbf350000,0xbf35bf80,0x3f350000,
0xbf358000,0xbf35bf80,0x3f358000,0x3f353f80,0x3f353f80,0xbf350000,0xbf35bf80,0x3f350000,0xbf358000,0xbf35bf80,0x3f358000,0x3f353f80,
0x3f353f80,0xbf350000,0xbf35bf80,0x3f350000,0xbf0ebf80,0x3f7b3ec4,0xbe483f35,0xbf55bf6d,0x3f558000,0x3e483f6d,0xbf7bbf35,0x3f0ebec4,
0x3f550000,0x3e483f6d,0xbf7bbf35,0x3f0ebec4,0x3f0e3f80,0xbf7bbec4,0x3e48bf35,0x3f553f6d,0x3f0e3f80,0xbf7bbec4,0x3e48bf35,0x3f553f6d,
0xbf558000,0xbe48bf6d,0x3f7b3f35,0xbf0e3ec4,0xbf550000,0xbe48bf6d,0x3f7b3f35,0xbf0e3ec4,0xbf0ebf80,0x3f7b3ec4,0xbe483f35,0xbf55bf6d,
0x3f6d8000,0xbec43f35,0xbec4bf80,0x3f6d3f35,0xbec4bf80,0x3f6d3f35,0xbf6d0000,0x3ec4bf35,0xbf6d8000,0x3ec4bf35,0x3ec43f80,0xbf6dbf35,
0x3ec43f80,0xbf6dbf35,0x3f6d0000,0xbec43f35,0x3f6d8000,0xbec43f35,0xbec4bf80,0x3f6d3f35,0xbec4bf80,0x3f6d3f35,0xbf6d0000,0x3ec4bf35,
0xbf6d8000,0x3ec4bf35,0x3ec43f80,0xbf6dbf35,0x3ec43f80,0xbf6dbf35,0x3f6d0000,0xbec43f35,0xbf7b0000,0x3f55bec4,0xbf0e3f35,0x3e48bf6d,
0xbe48bf80,0x3f0e3f6d,0xbf55bf35,0x3f7b3ec4,0xbe48bf80,0x3f0e3f6d,0xbf55bf35,0x3f7b3ec4,0x3f7b8000,0xbf553ec4,0x3f0ebf35,0xbe483f6d,
0x3f7b0000,0xbf553ec4,0x3f0ebf35,0xbe483f6d,0x3e483f80,0xbf0ebf6d,0x3f553f35,0xbf7bbec4,0x3e483f80,0xbf0ebf6d,0x3f553f35,0xbf7bbec4,
0xbf7b8000,0x3f55bec4,0xbf0e3f35,0x3e48bf6d,0x3f80,0xbf80,0x3f80,0xbf80,0x3f800000,0xbf800000,0x3f800000,0xbf800000,
0x3f80,0xbf80,0x3f80,0xbf80,0x3f800000,0xbf800000,0x3f800000,0xbf800000,0x3f80,0xbf80,0x3f80,0xbf80,
0x3f800000,0xbf800000,0x3f800000,0xbf800000,0x3f80,0xbf80,0x3f80,0xbf80,0x3f800000,0xbf800000,0x3f800000,0xbf800000,
0x3f7b0000,0xbf55bec4,0x3f0e3f35,0xbe48bf6d,0xbe483f80,0x3f0ebf6d,0xbf553f35,0x3f7bbec4,0xbe483f80,0x3f0ebf6d,0xbf553f35,0x3f7bbec4,
0xbf7b0000,0x3f553ec4,0xbf0ebf35,0x3e483f6d,0xbf7b0000,0x3f553ec4,0xbf0ebf35,0x3e483f6d,0x3e48bf80,0xbf0e3f6d,0x3f55bf35,0xbf7b3ec4,
0x3e48bf80,0xbf0e3f6d,0x3f55bf35,0xbf7b3ec4,0x3f7b0000,0xbf55bec4,0x3f0e3f35,0xbe48bf6d,0x3ec4bf80,0xbf6d3f35,0x3f6d0000,0xbec4bf35,
0xbf6d0000,0x3ec43f35,0x3ec4bf80,0xbf6d3f35,0xbec43f80,0x3f6dbf35,0xbf6d0000,0x3ec43f35,0x3f6d0000,0xbec4bf35,0xbec43f80,0x3f6dbf35,
0x3ec4bf80,0xbf6d3f35,0x3f6d0000,0xbec4bf35,0xbf6d0000,0x3ec43f35,0x3ec4bf80,0xbf6d3f35,0xbec43f80,0x3f6dbf35,0xbf6d0000,0x3ec43f35,
0x3f6d0000,0xbec4bf35,0xbec43f80,0x3f6dbf35,0x3f0ebf80,0xbf7b3ec4,0x3e483f35,0x3f55bf6d,0x3f550000,0x3e48bf6d,0xbf7b3f35,0x3f0e3ec4,
0x3f550000,0x3e48bf6d,0xbf7b3f35,0x3f0e3ec4,0xbf0e3f80,0x3f7bbec4,0xbe48bf35,0xbf553f6d,0xbf0e3f80,0x3f7bbec4,0xbe48bf35,0xbf553f6d,
0xbf550000,0xbe483f6d,0x3f7bbf35,0xbf0ebec4,0xbf550000,0xbe483f6d,0x3f7bbf35,0xbf0ebec4,0x3f0ebf80,0xbf7b3ec4,0x3e483f35,0x3f55bf6d,
0xbf353f80,0x3f350000,0x3f35bf80,0xbf350000,0x3f350000,0x3f35bf80,0xbf350000,0xbf353f80,0xbf353f80,0x3f350000,0x3f35bf80,0xbf350000,
0x3f350000,0x3f35bf80,0xbf350000,0xbf353f80,0xbf353f80,0x3f350000,0x3f35bf80,0xbf350000,0x3f350000,0x3f35bf80,0xbf350000,0xbf353f80,
0xbf353f80,0x3f350000,0x3f35bf80,0xbf350000,0x3f350000,0x3f35bf80,0xbf350000,0xbf353f80,0xbf0e0000,0xbf7b3f6d,0xbe483f35,0x3f55bec4,
0x3f55bf80,0xbe48bec4,0xbf7b3f35,0xbf0e3f6d,0x3f55bf80,0xbe48bec4,0xbf7b3f35,0xbf0e3f6d,0x3f0e0000,0x3f7bbf6d,0x3e48bf35,0xbf553ec4,
0x3f0e0000,0x3f7bbf6d,0x3e48bf35,0xbf553ec4,0xbf553f80,0x3e483ec4,0x3f7bbf35,0x3f0ebf6d,0xbf553f80,0x3e483ec4,0x3f7bbf35,0x3f0ebf6d,
0xbf0e0000,0xbf7b3f6d,0xbe483f35,0x3f55bec4,0x3f6dbf80,0x3ec4bf35,0xbec40000,0xbf6d3f35,0xbec40000,0xbf6d3f35,0xbf6d3f80,0xbec43f35,
0xbf6d3f80,0xbec43f35,0x3ec40000,0x3f6dbf35,0x3ec40000,0x3f6dbf35,0x3f6dbf80,0x3ec4bf35,0x3f6dbf80,0x3ec4bf35,0xbec40000,0xbf6d3f35,
0xbec40000,0xbf6d3f35,0xbf6d3f80,0xbec43f35,0xbf6d3f80,0xbec43f35,0x3ec40000,0x3f6dbf35,0x3ec40000,0x3f6dbf35,0x3f6dbf80,0x3ec4bf35,
0xbf7b3f80,0xbf553f6d,0xbf0e3f35,0xbe483ec4,0xbe480000,0xbf0e3ec4,0xbf553f35,0xbf7b3f6d,0xbe480000,0xbf0e3ec4,0xbf553f35,0xbf7b3f6d,
0x3f7bbf80,0x3f55bf6d,0x3f0ebf35,0x3e48bec4,0x3f7bbf80,0x3f55bf6d,0x3f0ebf35,0x3e48bec4,0x3e480000,0x3f0ebec4,0x3f55bf35,0x3f7bbf6d,
0x3e480000,0x3f0ebec4,0x3f55bf35,0x3f7bbf6d,0xbf7b3f80,0xbf553f6d,0xbf0e3f35,0xbe483ec4,0xbf808000,0x3f808000,0xbf808000,0x3f808000,
0x3f80,0xbf80,0x3f80,0xbf80,0xbf808000,0x3f808000,0xbf808000,0x3f808000,0x3f80,0xbf80,0x3f80,0xbf80,
0xbf808000,0x3f808000,0xbf808000,0x3f808000,0x3f80,0xbf80,0x3f80,0xbf80,0xbf808000,0x3f808000,0xbf808000,0x3f808000,
0x3f80,0xbf80,0x3f80,0xbf80,0xbe483f80,0x3f0ebf6d,0xbf553f35,0x3f7bbec4,0xbf7b8000,0x3f553ec4,0xbf0ebf35,0x3e483f6d,
0xbf7b0000,0x3f553ec4,0xbf0ebf35,0x3e483f6d,0x3e48bf80,0xbf0e3f6d,0x3f55bf35,0xbf7b3ec4,0x3e48bf80,0xbf0e3f6d,0x3f55bf35,0xbf7b3ec4,
0x3f7b8000,0xbf55bec4,0x3f0e3f35,0xbe48bf6d,0x3f7b0000,0xbf55bec4,0x3f0e3f35,0xbe48bf6d,0xbe483f80,0x3f0ebf6d,0xbf553f35,0x3f7bbec4,
0x3f6d8000,0xbec4bf35,0xbec43f80,0x3f6dbf35,0x3ec4bf80,0xbf6d3f35,0x3f6d0000,0xbec4bf35,0xbf6d8000,0x3ec43f35,0x3ec4bf80,0xbf6d3f35,
0xbec43f80,0x3f6dbf35,0xbf6d0000,0x3ec43f35,0x3f6d8000,0xbec4bf35,0xbec43f80,0x3f6dbf35,0x3ec4bf80,0xbf6d3f35,0x3f6d0000,0xbec4bf35,
0xbf6d8000,0x3ec43f35,0x3ec4bf80,0xbf6d3f35,0xbec43f80,0x3f6dbf35,0xbf6d0000,0x3ec43f35,0x3f550000,0x3e48bf6d,0xbf7b3f35,0x3f0e3ec4,
0xbf0e3f80,0x3f7bbec4,0xbe48bf35,0xbf553f6d,0xbf0e3f80,0x3f7bbec4,0xbe48bf35,0xbf553f6d,0xbf558000,0xbe483f6d,0x3f7bbf35,0xbf0ebec4,
0xbf550000,0xbe483f6d,0x3f7bbf35,0xbf0ebec4,0x3f0ebf80,0xbf7b3ec4,0x3e483f35,0x3f55bf6d,0x3f0ebf80,0xbf7b3ec4,0x3e483f35,0x3f55bf6d,
0x3f558000,0x3e48bf6d,0xbf7b3f35,0x3f0e3ec4,0xbf358000,0xbf353f80,0x3f358000,0x3f35bf80,0xbf353f80,0x3f350000,0x3f35bf80,0xbf350000,
0xbf358000,0xbf353f80,0x3f358000,0x3f35bf80,0xbf353f80,0x3f350000,0x3f35bf80,0xbf350000,0xbf358000,0xbf353f80,0x3f358000,0x3f35bf80,
0xbf353f80,0x3f350000,0x3f35bf80,0xbf350000,0xbf358000,0xbf353f80,0x3f358000,0x3f35bf80,0xbf353f80,0x3f350000,0x3f35bf80,0xbf350000,
0x3f55bf80,0xbe48bec4,0xbf7b3f35,0xbf0e3f6d,0x3f0e8000,0x3f7bbf6d,0x3e48bf35,0xbf553ec4,0x3f0e0000,0x3f7bbf6d,0x3e48bf35,0xbf553ec4,
0xbf553f80,0x3e483ec4,0x3f7bbf35,0x3f0ebf6d,0xbf553f80,0x3e483ec4,0x3f7bbf35,0x3f0ebf6d,0xbf0e8000,0xbf7b3f6d,0xbe483f35,0x3f55bec4,
0xbf0e0000,0xbf7b3f6d,0xbe483f35,0x3f55bec4,0x3f55bf80,0xbe48bec4,0xbf7b3f35,0xbf0e3f6d,0x3ec48000,0x3f6dbf35,0x3f6dbf80,0x3ec4bf35,
0x3f6dbf80,0x3ec4bf35,0xbec40000,0xbf6d3f35,0xbec48000,0xbf6d3f35,0xbf6d3f80,0xbec43f35,0xbf6d3f80,0xbec43f35,0x3ec40000,0x3f6dbf35,
0x3ec48000,0x3f6dbf35,0x3f6dbf80,0x3ec4bf35,0x3f6dbf80,0x3ec4bf35,0xbec40000,0xbf6d3f35,0xbec48000,0xbf6d3f35,0xbf6d3f80,0xbec43f35,
0xbf6d3f80,0xbec43f35,0x3ec40000,0x3f6dbf35,0xbe480000,0xbf0e3ec4,0xbf553f35,0xbf7b3f6d,0x3f7bbf80,0x3f55bf6d,0x3f0ebf35,0x3e48bec4,
0x3f7bbf80,0x3f55bf6d,0x3f0ebf35,0x3e48bec4,0x3e488000,0x3f0ebec4,0x3f55bf35,0x3f7bbf6d,0x3e480000,0x3f0ebec4,0x3f55bf35,0x3f7bbf6d,
0xbf7b3f80,0xbf553f6d,0xbf0e3f35,0xbe483ec4,0xbf7b3f80,0xbf553f6d,0xbf0e3f35,0xbe483ec4,0xbe488000,0xbf0e3ec4,0xbf553f35,0xbf7b3f6d,
0xbf803f80,0xbf803f80,0xbf803f80,0xbf803f80,0x0,0x0,0x0,0x0,0xbf803f80,0xbf803f80,0xbf803f80,0xbf803f80,
0x0,0x0,0x0,0x0,0xbf803f80,0xbf803f80,0xbf803f80,0xbf803f80,0x0,0x0,0x0,0x0,
0xbf803f80,0xbf803f80,0xbf803f80,0xbf803f80,0x0,0x0,0x0,0x0,0xbe480000,0xbf0e3ec4,0xbf553f35,0xbf7b3f6d,
0xbf7b3f80,0xbf553f6d,0xbf0e3f35,0xbe483ec4,0xbf7b3f80,0xbf553f6d,0xbf0e3f35,0xbe483ec4,0x3e480000,0x3f0ebec4,0x3f55bf35,0x3f7bbf6d,
0x3e480000,0x3f0ebec4,0x3f55bf35,0x3f7bbf6d,0x3f7bbf80,0x3f55bf6d,0x3f0ebf35,0x3e48bec4,0x3f7bbf80,0x3f55bf6d,0x3f0ebf35,0x3e48bec4,
0xbe480000,0xbf0e3ec4,0xbf553f35,0xbf7b3f6d,0x3f6dbf80,0x3ec4bf35,0xbec40000,0xbf6d3f35,0x3ec40000,0x3f6dbf35,0x3f6dbf80,0x3ec4bf35,
0xbf6d3f80,0xbec43f35,0x3ec40000,0x3f6dbf35,0xbec40000,0xbf6d3f35,0xbf6d3f80,0xbec43f35,0x3f6dbf80,0x3ec4bf35,0xbec40000,0xbf6d3f35,
0x3ec40000,0x3f6dbf35,0x3f6dbf80,0x3ec4bf35,0xbf6d3f80,0xbec43f35,0x3ec40000,0x3f6dbf35,0xbec40000,0xbf6d3f35,0xbf6d3f80,0xbec43f35,
0x3f55bf80,0xbe48bec4,0xbf7b3f35,0xbf0e3f6d,0xbf0e0000,0xbf7b3f6d,0xbe483f35,0x3f55bec4,0xbf0e0000,0xbf7b3f6d,0xbe483f35,0x3f55bec4,
0xbf553f80,0x3e483ec4,0x3f7bbf35,0x3f0ebf6d,0xbf553f80,0x3e483ec4,0x3f7bbf35,0x3f0ebf6d,0x3f0e0000,0x3f7bbf6d,0x3e48bf35,0xbf553ec4,
0x3f0e0000,0x3f7bbf6d,0x3e48bf35,0xbf553ec4,0x3f55bf80,0xbe48bec4,0xbf7b3f35,0xbf0e3f6d,0xbf353f80,0x3f350000,0x3f35bf80,0xbf350000,
0xbf350000,0xbf353f80,0x3f350000,0x3f35bf80,0xbf353f80,0x3f350000,0x3f35bf80,0xbf350000,0xbf350000,0xbf353f80,0x3f350000,0x3f35bf80,
0xbf353f80,0x3f350000,0x3f35bf80,0xbf350000,0xbf350000,0xbf353f80,0x3f350000,0x3f35bf80,0xbf353f80,0x3f350000,0x3f35bf80,0xbf350000,
0xbf350000,0xbf353f80,0x3f350000,0x3f35bf80,0x3f550000,0x3e48bf6d,0xbf7b3f35,0x3f0e3ec4,0x3f0ebf80,0xbf7b3ec4,0x3e483f35,0x3f55bf6d,
0x3f0ebf80,0xbf7b3ec4,0x3e483f35,0x3f55bf6d,0xbf550000,0xbe483f6d,0x3f7bbf35,0xbf0ebec4,0xbf550000,0xbe483f6d,0x3f7bbf35,0xbf0ebec4,
0xbf0e3f80,0x3f7bbec4,0xbe48bf35,0xbf553f6d,0xbf0e3f80,0x3f7bbec4,0xbe48bf35,0xbf553f6d,0x3f550000,0x3e48bf6d,0xbf7b3f35,0x3f0e3ec4,
0x3ec4bf80,0xbf6d3f35,0x3f6d0000,0xbec4bf35,0x3f6d0000,0xbec4bf35,0xbec43f80,0x3f6dbf35,0xbec43f80,0x3f6dbf35,0xbf6d0000,0x3ec43f35,
0xbf6d0000,0x3ec43f35,0x3ec4bf80,0xbf6d3f35,0x3ec4bf80,0xbf6d3f35,0x3f6d0000,0xbec4bf35,0x3f6d0000,0xbec4bf35,0xbec43f80,0x3f6dbf35,
0xbec43f80,0x3f6dbf35,0xbf6d0000,0x3ec43f35,0xbf6d0000,0x3ec43f35,0x3ec4bf80,0xbf6d3f35,0xbe483f80,0x3f0ebf6d,0xbf553f35,0x3f7bbec4,
0x3f7b0000,0xbf55bec4,0x3f0e3f35,0xbe48bf6d,0x3f7b0000,0xbf55bec4,0x3f0e3f35,0xbe48bf6d,0x3e48bf80,0xbf0e3f6d,0x3f55bf35,0xbf7b3ec4,
0x3e48bf80,0xbf0e3f6d,0x3f55bf35,0xbf7b3ec4,0xbf7b0000,0x3f553ec4,0xbf0ebf35,0x3e483f6d,0xbf7b0000,0x3f553ec4,0xbf0ebf35,0x3e483f6d,
0xbe483f80,0x3f0ebf6d,0xbf553f35,0x3f7bbec4,0x80008000,0x80008000,0x80008000,0x80008000,0xbf803f80,0xbf803f80,0xbf803f80,0xbf803f80,
0x80008000,0x80008000,0x80008000,0x80008000,0xbf803f80,0xbf803f80,0xbf803f80,0xbf803f80,0x80008000,0x80008000,0x80008000,0x80008000,
0xbf803f80,0xbf803f80,0xbf803f80,0xbf803f80,0x80008000,0x80008000,0x80008000,0x80008000,0xbf803f80,0xbf803f80,0xbf803f80,0xbf803f80,
0xbf7b3f80,0xbf553f6d,0xbf0e3f35,0xbe483ec4,0x3e488000,0x3f0ebec4,0x3f55bf35,0x3f7bbf6d,0x3e480000,0x3f0ebec4,0x3f55bf35,0x3f7bbf6d,
0x3f7bbf80,0x3f55bf6d,0x3f0ebf35,0x3e48bec4,0x3f7bbf80,0x3f55bf6d,0x3f0ebf35,0x3e48bec4,0xbe488000,0xbf0e3ec4,0xbf553f35,0xbf7b3f6d,
0xbe480000,0xbf0e3ec4,0xbf553f35,0xbf7b3f6d,0xbf7b3f80,0xbf553f6d,0xbf0e3f35,0xbe483ec4,0xbec48000,0xbf6d3f35,0xbf6d3f80,0xbec43f35,
0x3f6dbf80,0x3ec4bf35,0xbec40000,0xbf6d3f35,0x3ec48000,0x3f6dbf35,0x3f6dbf80,0x3ec4bf35,0xbf6d3f80,0xbec43f35,0x3ec40000,0x3f6dbf35,
0xbec48000,0xbf6d3f35,0xbf6d3f80,0xbec43f35,0x3f6dbf80,0x3ec4bf35,0xbec40000,0xbf6d3f35,0x3ec48000,0x3f6dbf35,0x3f6dbf80,0x3ec4bf35,
0xbf6d3f80,0xbec43f35,0x3ec40000,0x3f6dbf35,0xbf0e0000,0xbf7b3f6d,0xbe483f35,0x3f55bec4,0xbf553f80,0x3e483ec4,0x3f7bbf35,0x3f0ebf6d,
0xbf553f80,0x3e483ec4,0x3f7bbf35,0x3f0ebf6d,0x3f0e8000,0x3f7bbf6d,0x3e48bf35,0xbf553ec4,0x3f0e0000,0x3f7bbf6d,0x3e48bf35,0xbf553ec4,
0x3f55bf80,0xbe48bec4,0xbf7b3f35,0xbf0e3f6d,0x3f55bf80,0xbe48bec4,0xbf7b3f35,0xbf0e3f6d,0xbf0e8000,0xbf7b3f6d,0xbe483f35,0x3f55bec4,
0x3f358000,0x3f35bf80,0xbf358000,0xbf353f80,0xbf353f80,0x3f350000,0x3f35bf80,0xbf350000,0x3f358000,0x3f35bf80,0xbf358000,0xbf353f80,
0xbf353f80,0x3f350000,0x3f35bf80,0xbf350000,0x3f358000,0x3f35bf80,0xbf358000,0xbf353f80,0xbf353f80,0x3f350000,0x3f35bf80,0xbf350000,
0x3f358000,0x3f35bf80,0xbf358000,0xbf353f80,0xbf353f80,0x3f350000,0x3f35bf80,0xbf350000,0x3f0ebf80,0xbf7b3ec4,0x3e483f35,0x3f55bf6d,
0xbf558000,0xbe483f6d,0x3f7bbf35,0xbf0ebec4,0xbf550000,0xbe483f6d,0x3f7bbf35,0xbf0ebec4,0xbf0e3f80,0x3f7bbec4,0xbe48bf35,0xbf553f6d,
0xbf0e3f80,0x3f7bbec4,0xbe48bf35,0xbf553f6d,0x3f558000,0x3e48bf6d,0xbf7b3f35,0x3f0e3ec4,0x3f550000,0x3e48bf6d,0xbf7b3f35,0x3f0e3ec4,
0x3f0ebf80,0xbf7b3ec4,0x3e483f35,0x3f55bf6d,0xbf6d8000,0x3ec43f35,0x3ec4bf80,0xbf6d3f35,0x3ec4bf80,0xbf6d3f35,0x3f6d0000,0xbec4bf35,
0x3f6d8000,0xbec4bf35,0xbec43f80,0x3f6dbf35,0xbec43f80,0x3f6dbf35,0xbf6d0000,0x3ec43f35,0xbf6d8000,0x3ec43f35,0x3ec4bf80,0xbf6d3f35,
0x3ec4bf80,0xbf6d3f35,0x3f6d0000,0xbec4bf35,0x3f6d8000,0xbec4bf35,0xbec43f80,0x3f6dbf35,0xbec43f80,0x3f6dbf35,0xbf6d0000,0x3ec43f35,
0x3f7b0000,0xbf55bec4,0x3f0e3f35,0xbe48bf6d,0x3e48bf80,0xbf0e3f6d,0x3f55bf35,0xbf7b3ec4,0x3e48bf80,0xbf0e3f6d,0x3f55bf35,0xbf7b3ec4,
0xbf7b8000,0x3f553ec4,0xbf0ebf35,0x3e483f6d,0xbf7b0000,0x3f553ec4,0xbf0ebf35,0x3e483f6d,0xbe483f80,0x3f0ebf6d,0xbf553f35,0x3f7bbec4,
0xbe483f80,0x3f0ebf6d,0xbf553f35,0x3f7bbec4,0x3f7b8000,0xbf55bec4,0x3f0e3f35,0xbe48bf6d,0x3f80,0xbf80,0x3f80,0xbf80,
0xbf800000,0x3f800000,0xbf800000,0x3f800000,0x3f80,0xbf80,0x3f80,0xbf80,0xbf800000,0x3f800000,0xbf800000,0x3f800000,
0x3f80,0xbf80,0x3f80,0xbf80,0xbf800000,0x3f800000,0xbf800000,0x3f800000,0x3f80,0xbf80,0x3f80,0xbf80,
0xbf800000,0x3f800000,0xbf800000,0x3f800000,0xbf7b0000,0x3f55bec4,0xbf0e3f35,0x3e48bf6d,0x3e483f80,0xbf0ebf6d,0x3f553f35,0xbf7bbec4,
0x3e483f80,0xbf0ebf6d,0x3f553f35,0xbf7bbec4,0x3f7b0000,0xbf553ec4,0x3f0ebf35,0xbe483f6d,0x3f7b0000,0xbf553ec4,0x3f0ebf35,0xbe483f6d,
0xbe48bf80,0x3f0e3f6d,0xbf55bf35,0x3f7b3ec4,0xbe48bf80,0x3f0e3f6d,0xbf55bf35,0x3f7b3ec4,0xbf7b0000,0x3f55bec4,0xbf0e3f35,0x3e48bf6d,
0xbec4bf80,0x3f6d3f35,0xbf6d0000,0x3ec4bf35,0x3f6d0000,0xbec43f35,0xbec4bf80,0x3f6d3f35,0x3ec43f80,0xbf6dbf35,0x3f6d0000,0xbec43f35,
0xbf6d0000,0x3ec4bf35,0x3ec43f80,0xbf6dbf35,0xbec4bf80,0x3f6d3f35,0xbf6d0000,0x3ec4bf35,0x3f6d0000,0xbec43f35,0xbec4bf80,0x3f6d3f35,
0x3ec43f80,0xbf6dbf35,0x3f6d0000,0xbec43f35,0xbf6d0000,0x3ec4bf35,0x3ec43f80,0xbf6dbf35,0xbf0ebf80,0x3f7b3ec4,0xbe483f35,0xbf55bf6d,
0xbf550000,0xbe48bf6d,0x3f7b3f35,0xbf0e3ec4,0xbf550000,0xbe48bf6d,0x3f7b3f35,0xbf0e3ec4,0x3f0e3f80,0xbf7bbec4,0x3e48bf35,0x3f553f6d,
0x3f0e3f80,0xbf7bbec4,0x3e48bf35,0x3f553f6d,0x3f550000,0x3e483f6d,0xbf7bbf35,0x3f0ebec4,0x3f550000,0x3e483f6d,0xbf7bbf35,0x3f0ebec4,
0xbf0ebf80,0x3f7b3ec4,0xbe483f35,0xbf55bf6d,0x3f353f80,0xbf350000,0xbf35bf80,0x3f350000,0xbf350000,0xbf35bf80,0x3f350000,0x3f353f80,
0x3f353f80,0xbf350000,0xbf35bf80,0x3f350000,0xbf350000,0xbf35bf80,0x3f350000,0x3f353f80,0x3f353f80,0xbf350000,0xbf35bf80,0x3f350000,
0xbf350000,0xbf35bf80,0x3f350000,0x3f353f80,0x3f353f80,0xbf350000,0xbf35bf80,0x3f350000,0xbf350000,0xbf35bf80,0x3f350000,0x3f353f80,
0x3f0e0000,0x3f7b3f6d,0x3e483f35,0xbf55bec4,0xbf55bf80,0x3e48bec4,0x3f7b3f35,0x3f0e3f6d,0xbf55bf80,0x3e48bec4,0x3f7b3f35,0x3f0e3f6d,
0xbf0e0000,0xbf7bbf6d,0xbe48bf35,0x3f553ec4,0xbf0e0000,0xbf7bbf6d,0xbe48bf35,0x3f553ec4,0x3f553f80,0xbe483ec4,0xbf7bbf35,0xbf0ebf6d,
0x3f553f80,0xbe483ec4,0xbf7bbf35,0xbf0ebf6d,0x3f0e0000,0x3f7b3f6d,0x3e483f35,0xbf55bec4,0xbf6dbf80,0xbec4bf35,0x3ec40000,0x3f6d3f35,
0x3ec40000,0x3f6d3f35,0x3f6d3f80,0x3ec43f35,0x3f6d3f80,0x3ec43f35,0xbec40000,0xbf6dbf35,0xbec40000,0xbf6dbf35,0xbf6dbf80,0xbec4bf35,
0xbf6dbf80,0xbec4bf35,0x3ec40000,0x3f6d3f35,0x3ec40000,0x3f6d3f35,0x3f6d3f80,0x3ec43f35,0x3f6d3f80,0x3ec43f35,0xbec40000,0xbf6dbf35,
0xbec40000,0xbf6dbf35,0xbf6dbf80,0xbec4bf35,0x3f7b3f80,0x3f553f6d,0x3f0e3f35,0x3e483ec4,0x3e480000,0x3f0e3ec4,0x3f553f35,0x3f7b3f6d,
0x3e480000,0x3f0e3ec4,0x3f553f35,0x3f7b3f6d,0xbf7bbf80,0xbf55bf6d,0xbf0ebf35,0xbe48bec4,0xbf7bbf80,0xbf55bf6d,0xbf0ebf35,0xbe48bec4,
0xbe480000,0xbf0ebec4,0xbf55bf35,0xbf7bbf6d,0xbe480000,0xbf0ebec4,0xbf55bf35,0xbf7bbf6d,0x3f7b3f80,0x3f553f6d,0x3f0e3f35,0x3e483ec4,
0x3f808000,0xbf808000,0x3f808000,0xbf808000,0x3f80,0xbf80,0x3f80,0xbf80,0x3f808000,0xbf808000,0x3f808000,0xbf808000,
0x3f80,0xbf80,0x3f80,0xbf80,0x3f808000,0xbf808000,0x3f808000,0xbf808000,0x3f80,0xbf80,0x3f80,0xbf80,
0x3f808000,0xbf808000,0x3f808000,0xbf808000,0x3f80,0xbf80,0x3f80,0xbf80,0x3e483f80,0xbf0ebf6d,0x3f553f35,0xbf7bbec4,
0x3f7b8000,0xbf553ec4,0x3f0ebf35,0xbe483f6d,0x3f7b0000,0xbf553ec4,0x3f0ebf35,0xbe483f6d,0xbe48bf80,0x3f0e3f6d,0xbf55bf35,0x3f7b3ec4,
0xbe48bf80,0x3f0e3f6d,0xbf55bf35,0x3f7b3ec4,0xbf7b8000,0x3f55bec4,0xbf0e3f35,0x3e48bf6d,0xbf7b0000,0x3f55bec4,0xbf0e3f35,0x3e48bf6d,
0x3e483f80,0xbf0ebf6d,0x3f553f35,0xbf7bbec4,0xbf6d8000,0x3ec4bf35,0x3ec43f80,0xbf6dbf35,0xbec4bf80,0x3f6d3f35,0xbf6d0000,0x3ec4bf35,
0x3f6d8000,0xbec43f35,0xbec4bf80,0x3f6d3f35,0x3ec43f80,0xbf6dbf35,0x3f6d0000,0xbec43f35,0xbf6d8000,0x3ec4bf35,0x3ec43f80,0xbf6dbf35,
0xbec4bf80,0x3f6d3f35,0xbf6d0000,0x3ec4bf35,0x3f6d8000,0xbec43f35,0xbec4bf80,0x3f6d3f35,0x3ec43f80,0xbf6dbf35,0x3f6d0000,0xbec43f35,
0xbf550000,0xbe48bf6d,0x3f7b3f35,0xbf0e3ec4,0x3f0e3f80,0xbf7bbec4,0x3e48bf35,0x3f553f6d,0x3f0e3f80,0xbf7bbec4,0x3e48bf35,0x3f553f6d,
0x3f558000,0x3e483f6d,0xbf7bbf35,0x3f0ebec4,0x3f550000,0x3e483f6d,0xbf7bbf35,0x3f0ebec4,0xbf0ebf80,0x3f7b3ec4,0xbe483f35,0xbf55bf6d,
0xbf0ebf80,0x3f7b3ec4,0xbe483f35,0xbf55bf6d,0xbf558000,0xbe48bf6d,0x3f7b3f35,0xbf0e3ec4,0x3f358000,0x3f353f80,0xbf358000,0xbf35bf80,
0x3f353f80,0xbf350000,0xbf35bf80,0x3f350000,0x3f358000,0x3f353f80,0xbf358000,0xbf35bf80,0x3f353f80,0xbf350000,0xbf35bf80,0x3f350000,
0x3f358000,0x3f353f80,0xbf358000,0xbf35bf80,0x3f353f80,0xbf350000,0xbf35bf80,0x3f350000,0x3f358000,0x3f353f80,0xbf358000,0xbf35bf80,
0x3f353f80,0xbf350000,0xbf35bf80,0x3f350000,0xbf55bf80,0x3e48bec4,0x3f7b3f35,0x3f0e3f6d,0xbf0e8000,0xbf7bbf6d,0xbe48bf35,0x3f553ec4,
0xbf0e0000,0xbf7bbf6d,0xbe48bf35,0x3f553ec4,0x3f553f80,0xbe483ec4,0xbf7bbf35,0xbf0ebf6d,0x3f553f80,0xbe483ec4,0xbf7bbf35,0xbf0ebf6d,
0x3f0e8000,0x3f7b3f6d,0x3e483f35,0xbf55bec4,0x3f0e0000,0x3f7b3f6d,0x3e483f35,0xbf55bec4,0xbf55bf80,0x3e48bec4,0x3f7b3f35,0x3f0e3f6d,
0xbec48000,0xbf6dbf35,0xbf6dbf80,0xbec4bf35,0xbf6dbf80,0xbec4bf35,0x3ec40000,0x3f6d3f35,0x3ec48000,0x3f6d3f35,0x3f6d3f80,0x3ec43f35,
0x3f6d3f80,0x3ec43f35,0xbec40000,0xbf6dbf35,0xbec48000,0xbf6dbf35,0xbf6dbf80,0xbec4bf35,0xbf6dbf80,0xbec4bf35,0x3ec40000,0x3f6d3f35,
0x3ec48000,0x3f6d3f35,0x3f6d3f80,0x3ec43f35,0x3f6d3f80,0x3ec43f35,0xbec40000,0xbf6dbf35,0x3e480000,0x3f0e3ec4,0x3f553f35,0x3f7b3f6d,
0xbf7bbf80,0xbf55bf6d,0xbf0ebf35,0xbe48bec4,0xbf7bbf80,0xbf55bf6d,0xbf0ebf35,0xbe48bec4,0xbe488000,0xbf0ebec4,0xbf55bf35,0xbf7bbf6d,
0xbe480000,0xbf0ebec4,0xbf55bf35,0xbf7bbf6d,0x3f7b3f80,0x3f553f6d,0x3f0e3f35,0x3e483ec4,0x3f7b3f80,0x3f553f6d,0x3f0e3f35,0x3e483ec4,
0x3e488000,0x3f0e3ec4,0x3f553f35,0x3f7b3f6d,0x3f803f80,0x80008000,0x3f803f80,0x80008000,0x3f803f80,0x80008000,0x3f803f80,0x80008000,
0x3f803f80,0x80008000,0x3f803f80,0x80008000,0x3f803f80,0x80008000,0x3f803f80,0x80008000,0x3f803f80,0xbbc98000,0x3f803f80,0xbd62bd49,
0x3f803f80,0xbc97bc49,0x3f7f3f80,0xbd8abd7b,0x3f803f80,0xbcfbbcc9,0x3f7f3f7f,0xbda3bd97,0x3f803f80,0xbd30bd17,0x3f7f3f7f,0xbdbcbdb0,
0x3f803f80,0xbc498000,0x3f7e3f7f,0xbde2bdc9,0x3f803f80,0xbd17bcc9,0x3f7e3f7e,0xbe0abdfb,0x3f803f80,0xbd7bbd49,0x3f7d3f7d,0xbe23be16,
0x3f7f3f7f,0xbdb0bd97,0x3f7c3f7c,0xbe3bbe2f,0x3f803f80,0xbc978000,0x3f7c3f7d,0xbe29be16,0x3f803f80,0xbd62bd17,0x3f7b3f7c,0xbe4ebe3b,
0x3f7f3f7f,0xbdbcbd97,0x3f793f7a,0xbe73be60,0x3f7e3f7e,0xbe04bde2,0x3f763f78,0xbe8cbe82,0x3f803f80,0xbcc98000,0x3f7a3f7b,0xbe60be48,
0x3f7f3f80,0xbd97bd49,0x3f773f78,0xbe89be79,0x3f7e3f7f,0xbdfbbdc9,0x3f733f75,0xbea1be95,0x3f7c3f7d,0xbe2fbe16,0x3f6f3f71,0xbeb8beac,
0x3f803f80,0xbcfb8000,0x3f763f78,0xbe8cbe79,0x3f7f3f80,0xbdbcbd7b,0x3f723f74,0xbeaabe9b,0x3f7d3f7e,0xbe1cbdfb,0x3f6c3f6f,0xbec7beb8,
0x3f7a3f7c,0xbe5abe3b,0x3f653f69,0xbee3bed5,0x3f803f80,0xbd178000,0x3f723f75,0xbea7be95,0x3f7e3f7f,0xbde2bd97,0x3f6b3f6f,0xbecabeb8,
0x3f7c3f7d,0xbe3bbe16,0x3f633f67,0xbeecbedb,0x3f783f7a,0xbe82be60,0x3f5a3f5f,0xbf06befc,0x3f803f80,0xbd308000,0x3f6d3f71,0xbec1beac,
0x3f7e3f7f,0xbe04bdb0,0x3f643f69,0xbee9bed5,0x3f7a3f7c,0xbe5abe2f,0x3f593f5f,0xbf08befc,0x3f753f78,0xbe98be82,0x3f4d3f53,0xbf1abf11,
0x3f803f80,0xbd498000,0x3f673f6d,0xbedbbec4,0x3f7d3f7f,0xbe16bdc9,0x3f5c3f62,0xbf04bef1,0x3f783f7b,0xbe79be48,0x3f4e3f55,0xbf18bf0e,
0x3f713f75,0xbeacbe95,0x3f3e3f46,0xbf2cbf22,0x3f803f80,0xbd628000,0x3f613f67,0xbef4bedb,0x3f7c3f7e,0xbe29bde2,0x3f523f5a,0xbf12bf06,
0x3f763f7a,0xbe8cbe60,0x3f413f4a,0xbf28bf1d,0x3f6d3f72,0xbec1bea7,0x3f2d3f37,0xbf3dbf33,0x3f803f80,0xbd7b8000,0x3f5a3f62,0xbf06bef1,
0x3f7c3f7e,0xbe3bbdfb,0x3f483f51,0xbf20bf13,0x3f743f78,0xbe9bbe79,0x3f333f3e,0xbf37bf2c,0x3f693f6f,0xbed5beb8,0x3f1b3f27,0xbf4cbf42,
0x3f7f3f80,0xbd8a8000,0x3f523f5c,0xbf12bf04,0x3f7b3f7e,0xbe4ebe0a,0x3f3d3f48,0xbf2dbf20,0x3f723f77,0xbeaabe89,0x3f243f31,0xbf45bf39,
0x3f643f6b,0xbee9beca,0x3f083f16,0xbf59bf4f,0x3f7f3f80,0xbd978000,0x3f4a3f55,0xbf1dbf0e,0x3f7a3f7d,0xbe60be16,0x3f313f3e,0xbf39bf2c,
0x3f6f3f75,0xbeb8be95,0x3f133f22,0xbf51bf46,0x3f5f3f67,0xbefcbedb,0x3ee63f04,0xbf65bf5c,0x3f7f3f80,0xbda38000,0x3f413f4e,0xbf28bf18,
0x3f793f7d,0xbe73be23,0x3f243f33,0xbf45bf37,0x3f6c3f73,0xbec7bea1,0x3f023f13,0xbf5cbf51,0x3f593f63,0xbf08beec,0x3ebb3ee1,0xbf6ebf66,
0x3f7f3f80,0xbdb08000,0x3f373f46,0xbf33bf22,0x3f783f7c,0xbe82be2f,0x3f163f27,0xbf4fbf42,0x3f693f71,0xbed5beac,0x3ee13f04,0xbf66bf5c,
0x3f533f5f,0xbf11befc,0x3e8f3eb8,0xbf76bf6f,0x3f7f3f80,0xbdbc8000,0x3f2d3f3e,0xbf3dbf2c,0x3f763f7c,0xbe8cbe3b,0x3f083f1b,0xbf59bf4c,
0x3f653f6f,0xbee3beb8,0x3ebb3ee6,0xbf6ebf65,0x3f4d3f5a,0xbf1abf06,0x3e423e8f,0xbf7bbf76,0x3f7f3f80,0xbdc98000,0x3f223f35,0xbf46bf35,
0x3f753f7b,0xbe95be48,0x3ef13f0e,0xbf62bf55,0x3f623f6d,0xbef1bec4,0x3e953ec4,0xbf75bf6d,0x3f463f55,0xbf22bf0e,0x3dc93e48,0xbf7fbf7b,
0x3f7f3f80,0xbdd58000,0x3f173f2c,0xbf4fbf3e,0x3f743f7a,0xbe9ebe54,0x3ed23f01,0xbf69bf5d,0x3f5e3f6a,0xbeffbecf,0x3e5a3ea1,0xbf7abf73,
0x3f3f3f4f,0xbf2bbf16,0x3bc93de2,0xbf80bf7e,0x3f7e3f80,0xbde28000,0x3f0c3f22,0xbf57bf46,0x3f723f7a,0xbea7be60,0x3eb23ee6,0xbf70bf65,
0x3f5a3f67,0xbf06bedb,0x3e0a3e79,0xbf7ebf78,0x3f373f4a,0xbf33bf1d,0xbdb03cc9,0xbf7fbf80,0x3f7e3f80,0xbdee8000,0x3eff3f18,0xbf5ebf4e,
0x3f713f79,0xbeafbe6d,0x3e923eca,0xbf75bf6b,0x3f563f65,0xbf0dbee6,0x3d623e2f,0xbf80bf7c,0x3f2f3f44,0xbf3abf25,0xbe35bd7b,0xbf7cbf80,
0x3f7e3f80,0xbdfb8000,0x3ee63f0e,0xbf65bf55,0x3f6f3f78,0xbeb8be79,0x3e603eac,0xbf7abf71,0x3f513f62,0xbf13bef1,0xbcc93dc9,0xbf80bf7f,
0x3f273f3e,0xbf42bf2c,0xbe89be16,0xbf77bf7d,0x3f7e3f80,0xbe048000,0x3ecd3f04,0xbf6bbf5c,0x3f6d3f78,0xbec1be82,0x3e1c3e8f,0xbf7dbf76,
0x3f4d3f5f,0xbf1abefc,0xbdd53cc9,0xbf7fbf80,0x3f1f3f37,0xbf49bf33,0xbeb5be6d,0xbf6fbf79,0x3f7e3f80,0xbe0a8000,0x3eb23ef1,0xbf70bf62,
0x3f6b3f77,0xbecabe89,0x3db03e60,0xbf7fbf7a,0x3f483f5c,0xbf20bf04,0xbe3bbd49,0xbf7cbf80,0x3f163f31,0xbf4fbf39,0xbee1bea1,0xbf66bf73,
0x3f7d3f80,0xbe108000,0x3e983edb,0xbf75bf67,0x3f693f76,0xbed2be8f,0x3c973e23,0xbf80bf7d,0x3f433f58,0xbf26bf09,0xbe86bdfb,0xbf77bf7e,
0x3f0d3f2a,0xbf56bf40,0xbf05beca,0xbf5bbf6b,0x3f7d3f80,0xbe168000,0x3e793ec4,0xbf78bf6d,0x3f673f75,0xbedbbe95,0xbd493dc9,0xbf80bf7f,
0x3f3e3f55,0xbf2cbf0e,0xbeacbe48,0xbf71bf7b,0x3f043f22,0xbf5cbf46,0xbf18bef1,0xbf4ebf62,0x3f7d3f80,0xbe1c8000,0x3e423eac,0xbf7bbf71,
0x3f653f74,0xbee3be9b,0xbdee3d17,0xbf7ebf80,0x3f383f51,0xbf32bf13,0xbed2be89,0xbf69bf77,0x3ef43f1b,0xbf61bf4c,0xbf2bbf0c,0xbf3fbf57,
0x3f7d3f80,0xbe238000,0x3e0a3e95,0xbf7ebf75,0x3f633f73,0xbeecbea1,0xbe3bbcc9,0xbf7cbf80,0x3f333f4e,0xbf37bf18,0xbef7beac,0xbf60bf71,
0x3ee13f13,0xbf66bf51,0xbf3cbf1d,0xbf2ebf4a,0x3f7c3f80,0xbe298000,0x3da33e79,0xbf7fbf78,0x3f613f72,0xbef4bea7,0xbe7fbdb0,0xbf78bf7f,
0x3f2d3f4a,0xbf3dbf1d,0xbf0dbecf,0xbf56bf6a,0x3ecd3f0c,0xbf6bbf57,0xbf4bbf2e,0xbf1cbf3c,0x3f7c3f80,0xbe2f8000,0x3cc93e48,0xbf80bf7b,
0x3f5f3f71,0xbefcbeac,0xbea1be16,0xbf73bf7d,0x3f273f46,0xbf42bf22,0xbf1dbef1,0xbf4abf62,0x3eb83f04,0xbf6fbf5c,0xbf58bf3e,0xbf09bf2c,
0x3f7c3f80,0xbe358000,0xbcfb3e16,0xbf80bf7d,0x3f5c3f70,0xbf02beb2,0xbec1be54,0xbf6dbf7a,0x3f213f42,0xbf47bf27,0xbf2dbf09,0xbf3dbf58,
0x3ea43ef7,0xbf73bf60,0xbf64bf4c,0xbee9bf1b,0x3f7c3f80,0xbe3b8000,0xbdb03dc9,0xbf7fbf7f,0x3f5a3f6f,0xbf06beb8,0xbee1be89,0xbf66bf77,
0x3f1b3f3e,0xbf4cbf2c,0xbf3cbf18,0xbf2ebf4e,0x3e8f3ee6,0xbf76bf65,0xbf6ebf58,0xbebebf09,0x3f7b3f80,0xbe428000,0xbe103d49,0xbf7dbf80,
0x3f573f6e,0xbf0abebe,0xbeffbea7,0xbf5ebf72,0x3f153f39,0xbf50bf31,0xbf49bf27,0xbf1fbf42,0x3e733ed5,0xbf79bf69,0xbf75bf63,0xbe92beec,
0x3f803f80,0x80008000,0x3f803f80,0x80008000,0x3f803f80,0x80008000,0x3f803f80,0x80008000,0x3f803f80,0x80008000,0x3f803f80,0x80008000,
0x3f803f80,0x80008000,0x3f803f80,0x80008000,0x3f7f3f7f,0xbdd5bdc9,0x3f7d3f7d,0xbe1cbe16,0x3f7e3f7e,0xbdeebde2,0x3f7c3f7d,0xbe29be23,
0x3f7e3f7e,0xbe04bdfb,0x3f7c3f7c,0xbe35be2f,0x3f7d3f7e,0xbe10be0a,0x3f7b3f7c,0xbe42be3b,0x3f7a3f7b,0xbe54be48,0x3f743f75,0xbe9bbe95,
0x3f793f7a,0xbe6dbe60,0x3f723f73,0xbea7bea1,0x3f783f78,0xbe82be79,0x3f703f71,0xbeb2beac,0x3f763f77,0xbe8fbe89,0x3f6e3f6f,0xbebebeb8,
0x3f743f75,0xbe9ebe95,0x3f653f67,0xbee3bedb,0x3f713f72,0xbeafbea7,0x3f613f63,0xbef4beec,0x3f6d3f6f,0xbec1beb8,0x3f5c3f5f,0xbf02befc,
0x3f693f6b,0xbed2beca,0x3f573f5a,0xbf0abf06,0x3f6a3f6d,0xbecfbec4,0x3f513f55,0xbf13bf0e,0x3f653f67,0xbee6bedb,0x3f4a3f4e,0xbf1dbf18,
0x3f5f3f62,0xbefcbef1,0x3f423f46,0xbf27bf22,0x3f583f5c,0xbf09bf04,0x3f393f3e,0xbf31bf2c,0x3f5e3f62,0xbeffbef1,0x3f383f3e,0xbf32bf2c,
0x3f563f5a,0xbf0dbf06,0x3f2d3f33,0xbf3dbf37,0x3f4d3f51,0xbf1abf13,0x3f213f27,0xbf47bf42,0x3f433f48,0xbf26bf20,0x3f153f1b,0xbf50bf4c,
0x3f4f3f55,0xbf16bf0e,0x3f1b3f22,0xbf4cbf46,0x3f443f4a,0xbf25bf1d,0x3f0c3f13,0xbf57bf51,0x3f373f3e,0xbf33bf2c,0x3ef73f04,0xbf60bf5c,
0x3f2a3f31,0xbf40bf39,0x3ed53ee6,0xbf69bf65,0x3f3f3f46,0xbf2bbf22,0x3ef43f04,0xbf61bf5c,0x3f2f3f37,0xbf3abf33,0x3ecd3ee1,0xbf6bbf66,
0x3f1f3f27,0xbf49bf42,0x3ea43eb8,0xbf73bf6f,0x3f0d3f16,0xbf56bf4f,0x3e733e8f,0xbf79bf76,0x3f2c3f35,0xbf3ebf35,0x3eac3ec4,0xbf71bf6d,
0x3f183f22,0xbf4ebf46,0x3e793e95,0xbf78bf75,0x3f043f0e,0xbf5cbf55,0x3e163e48,0xbf7dbf7b,0x3edb3ef1,0xbf67bf62,0x3d493dc9,0xbf80bf7f,
0x3f173f22,0xbf4fbf46,0x3e423e79,0xbf7bbf78,0x3eff3f0c,0xbf5ebf57,0x3da33e0a,0xbf7fbf7e,0x3ecd3ee6,0xbf6bbf65,0xbcfb3cc9,0xbf80bf80,
0x3e983eb2,0xbf75bf70,0xbe10bdb0,0xbf7dbf7f,0x3f013f0e,0xbf5dbf55,0x3d173dc9,0xbf80bf7f,0x3eca3ee6,0xbf6bbf65,0xbdb0bcc9,0xbf7fbf80,
0x3e8f3eac,0xbf76bf71,0xbe54be16,0xbf7abf7d,0x3e233e60,0xbf7dbf7a,0xbea7be89,0xbf72bf77,0x3ed23ef1,0xbf69bf62,0xbdeebd49,0xbf7ebf80,
0x3e923eb2,0xbf75bf70,0xbe7fbe3b,0xbf78bf7c,0x3e1c3e60,0xbf7dbf7a,0xbec1bea1,0xbf6dbf73,0x3c973db0,0xbf80bf7f,0xbeffbee1,0xbf5ebf66,
0x3ea13ec4,0xbf73bf6d,0xbe89be48,0xbf77bf7b,0x3e2f3e79,0xbf7cbf78,0xbecfbeac,0xbf6abf71,0x3cc93dc9,0xbf80bf7f,0xbf09bef1,0xbf58bf62,
0xbdfbbd49,0xbf7ebf80,0xbf27bf18,0xbf42bf4e,0x3e5a3e95,0xbf7abf75,0xbed2beac,0xbf69bf71,0x3d623e0a,0xbf80bf7e,0xbf0dbef7,0xbf56bf60,
0xbdd5bcc9,0xbf7fbf80,0xbf2dbf1d,0xbf3dbf4a,0xbe86be3b,0xbf77bf7c,0xbf49bf3c,0xbf1fbf2e,0x3de23e48,0xbf7ebf7b,0xbf0cbef1,0xbf57bf62,
0xbd7b3cc9,0xbf80bf80,0xbf2ebf1d,0xbf3cbf4a,0xbe6dbe16,0xbf79bf7d,0xbf4cbf3e,0xbf1bbf2c,0xbecabea1,0xbf6bbf73,0xbf63bf58,0xbeecbf09,
0x3bc93dc9,0xbf80bf7f,0xbf2bbf18,0xbf3fbf4e,0xbe35bdb0,0xbf7cbf7f,0xbf4bbf3c,0xbf1cbf2e,0xbeb5be89,0xbf6fbf77,0xbf64bf58,0xbee9bf09,
0xbf05bee1,0xbf5bbf66,0xbf75bf6e,0xbe92bebe,0xbdc90000,0xbf7fbf80,0xbf46bf35,0xbf22bf35,0xbe95be48,0xbf75bf7b,0xbf62bf55,0xbef1bf0e,
0xbef1bec4,0xbf62bf6d,0xbf75bf6d,0xbe95bec4,0xbf22bf0e,0xbf46bf55,0xbf7fbf7b,0xbdc9be48,0xbe4ebdc9,0xbf7bbf7f,0xbf5cbf4e,0xbf02bf18,
0xbecdbe9b,0xbf6bbf74,0xbf73bf69,0xbea4bed5,0xbf15befc,0xbf50bf5f,0xbf7ebf7a,0xbdeebe60,0xbf3dbf2a,0xbf2dbf40,0xbf7fbf80,0x3dbcbc49,
0xbe9bbe48,0xbf74bf7b,0xbf6ebf62,0xbebebef1,0xbf01becf,0xbf5dbf6a,0xbf7dbf77,0xbe23be89,0xbf2ebf18,0xbf3cbf4e,0xbf80bf80,0x3d7bbd49,
0xbf53bf42,0xbf11bf27,0xbf76bf7c,0x3e8f3e2f,0xbecdbe95,0xbf6bbf75,0xbf79bf71,0xbe66beac,0xbf1abf01,0xbf4dbf5d,0xbf80bf7e,0x3bc9bde2,
0xbf45bf31,0xbf24bf39,0xbf79bf7e,0x3e733dfb,0xbf65bf57,0xbee3bf0c,0xbf64bf70,0x3ee93eb2,0xbefcbec4,0xbf5fbf6d,0xbf7fbf7b,0xbd97be48,
0xbf31bf18,0xbf39bf4e,0xbf7cbf80,0x3e2f3d49,0xbf58bf46,0xbf09bf22,0xbf6abf75,0x3ecf3e95,0xbf73bf67,0xbea1bedb,0xbf4abf5c,0x3f1d3f04,
0xbf15bef1,0xbf50bf62,0xbf7fbf80,0x3da3bd49,0xbf45bf2e,0xbf24bf3c,0xbf72bf7a,0x3eaa3e54,0xbf68bf58,0xbed8bf09,0xbf54bf65,0x3f103ee6,
0xbf7cbf74,0xbe35be9b,0xbf28bf40,0x3f413f2a,0xbf2abf0e,0xbf40bf55,0xbf79bf7f,0x3e6d3dc9,0xbf57bf42,0xbf0cbf27,0xbf60bf6f,0x3ef73eb8,
0xbf74bf67,0xbe9bbedb,0xbf37bf4e,0x3f333f18,0xbf80bf7c,0xbd17be2f,0xbf01bf1d,0x3f5d3f4a,0xbf3dbf22,0xbf2dbf46,0xbf6dbf78,0x3ec13e79,
0xbf65bf53,0xbee3bf11,0xbf49bf5d,0x3f1f3f01,0xbf7cbf73,0xbe35bea1,0xbf15bf31,0x3f503f39,0xbf7fbf80,0x3dd5bd17,0xbeaabeec,0x3f723f63,
0xbf4ebf35,0xbf18bf35,0xbf5cbf6d,0x3f043ec4,0xbf71bf62,0xbeacbef1,0xbf2cbf46,0x3f3e3f22,0xbf80bf7b,0xbd49be48,0xbedbbf0e,0x3f673f55,
0xbf78bf7f,0x3e793dc9,0xbe16be95,0x3f7d3f75,0xbf5cbf46,0xbf02bf22,0xbf45bf5c,0x3f243f04,0xbf79bf6e,0xbe66bebe,0xbf0abf2a,0x3f573f40,
0xbf7fbf7f,0x3da3bd97,0xbe86becf,0x3f773f6a,0xbf6dbf79,0x3ec13e6d,0x3d30bde2,0x3f803f7e,0xbf69bf55,0xbed5bf0e,0xbf2abf46,0x3f403f22,
0xbf7ebf77,0xbde2be89,0xbecabf09,0x3f6b3f58,0xbf7abf80,0x3e543d49,0xbdb0be79,0x3f7f3f78,0xbf5dbf6f,0x3f013eb8,0x3e6d3d97,0x3f793f7f,
0xbf73bf62,0xbea4bef1,0xbf0abf2c,0x3f573f3e,0xbf80bf7d,0x3bc9be23,0xbe73beca,0x3f793f6b,0xbf72bf7c,0x3eaa3e2f,0x3dbcbd97,0x3f7f3f7f,
0xbf49bf60,0x3f1f3ef7,0x3ed23e82,0x3f693f78,0xbf7abf6d,0xbe60bec4,0xbecfbf0e,0x3f6a3f55,0xbf7ebf80,0x3dfbbd49,0xbd97be79,0x3f7f3f78,
0xbf65bf75,0x3ee63e95,0x3e893dc9,0x3f773f7f,0xbf31bf4e,0x3f393f18,0x3f133edb,0x3f513f67,0xbf7ebf75,0xbdeebe95,0xbe86bedb,0x3f773f67,
0xbf79bf80,0x3e733d7b,0x3dbcbdb0,0x3f7f3f7f,0xbf54bf6a,0x3f103ecf,0x3ede3e89,0x3f673f77,0xbf15bf37,0x3f503f33,0x3f383f16,0x3f323f4f,
0xbf80bf7b,0xbc49be48,0xbde2be95,0x3f7e3f75,0xbf70bf7c,0x3eb23e2f,0x3e823d97,0x3f783f7f,0xbf40bf5c,0x3f2a3f04,0x3f163edb,0x3f4f3f67,
0xbeecbf1d,0x3f633f4a,0x3f573f39,0x3f0c3f31,0xbf7fbf7f,0x3dbcbdc9,0x3d30be16,0x3f803f7d,0xbf64bf76,0x3ee93e8f,0x3ed23e6d,0x3f693f79,
0xbf28bf4a,0x3f413f1d,0x3f383f13,0x3f323f51,0xbeaabf01,0x3f723f5d,0x3f6d3f57,0x3ec13f0c,
};
__device__ const __align__(128) uint64_t c_inv[16384] = {
0x3f003f003f003f00,0x3f003f003f003f00,0x3f003f003f003f00,0x3f003f003f003f00,0x3f003f003f003f00,0x3f003f003f003f00,0x3f003f003f003f00,0x3f003f003f003f00,
0xbf003f00bf003f00,0xbf003f00bf003f00,0xbf003f00bf003f00,0xbf003f00bf003f00,0xbf003f00bf003f00,0xbf003f00bf003f00,0xbf003f00bf003f00,0xbf003f00bf003f00,
0x3f773f783f7a3f7b,0x3f6f3f713f733f75,0x3f7f3f803f803f80,0x3f7c3f7d3f7e3f7f,0x3f4a3f4e3f513f55,0x3f393f3e3f423f46,0x3f653f673f6a3f6d,0x3f583f5c3f5f3f62,
0xbe89be79be60be48,0xbeb8beacbea1be95,0xbd97bd49bcc98000,0xbe2fbe16bdfbbdc9,0xbf1dbf18bf13bf0e,0xbf31bf2cbf27bf22,0xbee6bedbbecfbec4,0xbf09bf04befcbef1,
0x3f183f223f2c3f35,0x3edb3ef13f043f0e,0x3e793e953eac3ec4,0x3d493dc93e163e48,0x3f7d3f7f3f803f80,0x3f713f753f783f7b,0x3f5c3f623f673f6d,0x3f3e3f463f4e3f55,
0xbf4ebf46bf3ebf35,0xbf67bf62bf5cbf55,0xbf78bf75bf71bf6d,0xbf80bf7fbf7dbf7b,0xbe16bdc9bd498000,0xbeacbe95be79be48,0xbf04bef1bedbbec4,0xbf2cbf22bf18bf0e,
0xbecfbeacbe89be48,0xbf27bf18bf09bef1,0x3e2f3e793ea13ec4,0xbdfbbd493cc93dc9,0x3f313f3e3f4a3f55,0x3ee63f043f133f22,0x3f7a3f7d3f7f3f80,0x3f5f3f673f6f3f75,
0xbf6abf71bf77bf7b,0xbf42bf4ebf58bf62,0xbf7cbf78bf73bf6d,0xbf7ebf80bf80bf7f,0xbf39bf2cbf1dbf0e,0xbf65bf5cbf51bf46,0xbe60be16bd978000,0xbefcbedbbeb8be95,
0x3f753f7b3f7f3f80,0x3f463f553f623f6d,0x3ef13f0e3f223f35,0x3dc93e483e953ec4,0xbe95be48bdc90000,0xbf22bf0ebef1bec4,0xbf62bf55bf46bf35,0xbf7fbf7bbf75bf6d,
0xbe95be48bdc98000,0xbf22bf0ebef1bec4,0xbf62bf55bf46bf35,0xbf7fbf7bbf75bf6d,0xbf75bf7bbf7fbf80,0xbf46bf55bf62bf6d,0xbef1bf0ebf22bf35,0xbdc9be48be95bec4,
0x3e603eac3ee63f0e,0xbe89be16bcc93dc9,0x3f6f3f783f7e3f80,0x3f273f3e3f513f62,0xbf7cbf80bf7fbf7b,0xbf4abf5cbf6abf75,0xbf31bf18befcbec4,0xbf73bf67bf58bf46,
0xbf7abf71bf65bf55,0xbf77bf7dbf80bf7f,0xbeb8be79bdfb8000,0xbf42bf2cbf13bef1,0x3e2f3d49bd97be48,0x3f1d3f043ecf3e95,0xbf39bf4ebf5fbf6d,0xbea1bedbbf09bf22,
0xbf71bf62bf4ebf35,0xbf78bf7fbf80bf7b,0xbf2cbf46bf5cbf6d,0xbe16be95bedbbf0e,0x3f673f753f7d3f80,0x3f043f223f3e3f55,0xbd493dc93e793ec4,0xbf18bef1beacbe48,
0xbeacbef1bf18bf35,0x3e793dc9bd49be48,0x3f3e3f223f043ec4,0x3f7d3f753f673f55,0xbedbbe95be168000,0xbf5cbf46bf2cbf0e,0xbf80bf7fbf78bf6d,0xbf4ebf62bf71bf7b,
0xbd97be79becfbf0e,0x3f133edb3e893dc9,0xbf7ebf80bf7abf6d,0xbf31bf4ebf65bf75,0xbea1be163cc93e48,0xbf58bf3ebf1dbef1,0x3f5f3f713f7c3f80,0x3eb83f043f273f46,
0x3f7f3f783f6a3f55,0x3f513f673f773f7f,0x3dfbbd49be60bec4,0x3f393f183ee63e95,0xbf73bf7dbf80bf7b,0xbf09bf2cbf4abf62,0xbefcbeacbe2f8000,0xbf6fbf5cbf42bf22,
0x3f553f6d3f7b3f80,0x3e483ec43f0e3f35,0xbf0ebec4be480000,0xbf7bbf6dbf55bf35,0xbf55bf6dbf7bbf80,0xbe48bec4bf0ebf35,0x3f0e3ec43e480000,0x3f7b3f6d3f553f35,
0xbf0ebec4be488000,0xbf7bbf6dbf55bf35,0xbf55bf6dbf7bbf80,0xbe48bec4bf0ebf35,0x3f0e3ec43e488000,0x3f7b3f6d3f553f35,0x3f553f6d3f7b3f80,0x3e483ec43f0e3f35,
0xbf42bf18becfbe48,0xbf7cbf80bf77bf62,0x3f4a3f673f7a3f80,0x3cc93e793ee63f22,0x3f733f5c3f393f0e,0x3f583f713f7e3f7f,0xbefcbf2cbf51bf6d,0x3eb83e16bd97be95,
0xbf27bf4ebf6abf7b,0x3e2fbd49be89bef1,0xbf1dbedbbe608000,0xbf80bf78bf65bf46,0x3ea13f043f313f55,0xbf09beacbdfb3dc9,0x3f5f3f3e3f133ec4,0x3f6f3f7d3f7f3f75,
0xbd49be95bf04bf35,0x3f4e3f223edb3e48,0x3f713f7f3f7d3f6d,0x3e793ef13f2c3f55,0x3f3e3f623f783f80,0xbe163dc93eac3f0e,0xbf67bf46bf18bec4,0xbf5cbf75bf80bf7b,
0x3f803f753f5c3f35,0x3f183f463f673f7b,0xbeacbdc93e163ec4,0xbf78bf62bf3ebf0e,0xbf2cbef1be798000,0xbf7dbf7fbf71bf55,0xbedbbf22bf4ebf6d,0x3f043e953d49be48,
0x3f093f3e3f653f7b,0xbefcbe793cc93e95,0x3ecf3e16bdfbbec4,0x3f7f3f713f513f22,0xbf7cbf67bf42bf0e,0xbf1dbf4ebf6fbf7f,0x3f313f5c3f773f80,0xbea1bd493e603ef1,
0xbf58bf2cbee6be48,0xbf5fbf78bf80bf75,0x3f6a3f7d3f7e3f6d,0x3d973eac3f133f46,0xbe2fbedbbf27bf55,0x3f4a3f183eb83dc9,0xbf39bf04be898000,0xbf73bf80bf7abf62,
0x3f223f553f753f80,0xbef1be483dc93ec4,0xbf7fbf7bbf62bf35,0xbe95bf0ebf46bf6d,0x3f463f0e3e950000,0x3f623f7b3f7f3f6d,0xbdc93e483ef13f35,0xbf75bf55bf22bec4,
0xbf46bf0ebe958000,0xbf62bf7bbf7fbf6d,0x3dc9be48bef1bf35,0x3f753f553f223ec4,0x3f223f553f753f80,0xbef1be483dc93ec4,0xbf7fbf7bbf62bf35,0xbe95bf0ebf46bf6d,
0xbf6fbf80bf77bf55,0x3d97be79bf09bf46,0x3f133f4e3f733f80,0xbf1dbeacbcc93e95,0xbf31bedbbdfb3e48,0xbf65bf7dbf7cbf62,0x3f7a3f5c3f273ec4,0x3efc3f3e3f6a3f7f,
0x3eb83d49be89bf0e,0x3f7f3f783f583f22,0xbf51bf18bea18000,0xbf4abf71bf80bf75,0xbf39bf67bf7ebf7b,0x3ee63e16be2fbef1,0x3e603f043f423f6d,0xbf5fbf2cbecfbdc9,
0x3f783f7f3f673f35,0xbd493e953f183f55,0xbf7dbf62bf2cbec4,0xbeacbf22bf5cbf7b,0x3f043f463f713f80,0xbf3ebef1be163e48,0xbf4ebf75bf80bf6d,0x3edb3dc9be79bf0e,
0xbe793dc93edb3f35,0xbf80bf75bf4ebf0e,0xbe16bef1bf3ebf6d,0x3f713f463f043e48,0xbf5cbf22beac8000,0xbf2cbf62bf7dbf7b,0x3f183e95bd49bec4,0x3f673f7f3f783f55,
0xbf5fbf7dbf7abf55,0x3ecf3d49bea1bf22,0x3f423f713f803f6d,0xbf13be793dfb3ef1,0xbf1dbf5cbf7cbf7b,0x3f393edb3d97be95,0x3ee63f3e3f6f3f80,0xbf58bf18be893dc9,
0x3efc3e16be60bf0e,0x3f6a3f803f733f46,0xbf27beac3cc93ec4,0xbf51bf78bf7ebf62,0x3f4a3f043e2fbe48,0x3f313f673f7f3f75,0xbf65bf2cbeb88000,0xbf09bf4ebf77bf7f,
0x3ec43f353f6d3f80,0xbf6dbf35bec40000,0xbec4bf35bf6dbf80,0x3f6d3f353ec40000,0x3ec43f353f6d3f80,0xbf6dbf35bec40000,0xbec4bf35bf6dbf80,0x3f6d3f353ec40000,
0xbf6dbf35bec48000,0xbec4bf35bf6dbf80,0x3f6d3f353ec48000,0x3ec43f353f6d3f80,0xbf6dbf35bec48000,0xbec4bf35bf6dbf80,0x3f6d3f353ec48000,0x3ec43f353f6d3f80,
0xbdfbbf04bf51bf7b,0x3f803f673f273e95,0x3ea13f2c3f6a3f80,0xbf7abf4ebefcbdc9,0x3e89be16bf09bf55,0x3f6f3f803f653f22,0xbd973eac3f313f6d,0xbf7cbf78bf4abef1,
0x3f7e3f5c3f133e48,0x3cc93edb3f423f75,0xbf73bf3ebecf8000,0xbe60bf18bf5fbf7f,0x3f773f7d3f583f0e,0xbeb83d493ee63f46,0xbf7fbf71bf39bec4,0x3e2fbe79bf1dbf62,
0xbf04bdc93eac3f35,0xbf3ebf75bf7dbf55,0x3f4e3ef13d49bec4,0x3edb3f463f783f7b,0x3e793f223f673f80,0xbf80bf62bf18be48,0x3e16be95bf2cbf6d,0x3f713f7f3f5c3f0e,
0xbf5cbf7fbf71bf35,0x3f2c3e95be16bf0e,0x3f183f623f803f6d,0xbf67bf22be793e48,0xbf78bf46bedb8000,0xbd49bef1bf4ebf7b,0x3f7d3f753f3e3ec4,0xbeac3dc93f043f55,
0x3f803f673f1d3e48,0xbea13e163f133f62,0xbf58bf04bd973ec4,0xbe89bf2cbf6fbf7f,0x3ecfbd49befcbf55,0x3f423f783f7a3f46,0x3e2f3f183f653f80,0xbf7ebf71bf31be95,
0xbcc93edb3f4a3f7b,0xbf73bf7dbf51bef1,0xbf09bf5cbf7fbf6d,0x3f773f3e3eb8bdc9,0x3f6a3f803f5f3f0e,0xbf27be793e603f22,0xbf7cbf4ebee68000,0x3dfbbeacbf39bf75,
0x3dc93f0e3f623f80,0xbf75bf7bbf46bec4,0x3f223e48be95bf35,0x3ef13f553f7f3f6d,0xbf7fbf55bef10000,0x3e95be48bf22bf6d,0x3f463f7b3f753f35,0xbf62bf0ebdc93ec4,
0xbf7fbf55bef18000,0x3e95be48bf22bf6d,0x3f463f7b3f753f35,0xbf62bf0ebdc93ec4,0xbdc9bf0ebf62bf80,0x3f753f7b3f463ec4,0xbf22be483e953f35,0xbef1bf55bf7fbf6d,
0x3f513edbbd97bf0e,0x3dfb3f183f6a3f7f,0x3cc93f043f5f3f80,0xbf65bf80bf58bef1,0x3e603f2c3f733f7b,0xbf77bf78bf39be95,0xbf6fbf7dbf4abec4,0x3f423eacbe2fbf22,
0x3f133f673f7f3f55,0xbf7ebf4ebecf3dc9,0xbf80bf5cbefc8000,0x3ee6bd49bf09bf62,0xbf7abf3ebea13e48,0x3e89be79bf31bf75,0x3eb8be16bf1dbf6d,0x3f273f713f7c3f46,
0xbf2cbf75bf78bf35,0x3f7d3f463eacbe48,0xbedb3dc93f183f6d,0xbf04bf62bf80bf55,0xbd493ef13f5c3f80,0xbf4ebf7fbf67bf0e,0x3f713f223e16bec4,0xbe793e953f3e3f7b,
0x3f3e3e95be79bf35,0x3e163f223f713f7b,0xbf67bf7fbf4ebec4,0x3f5c3ef1bd49bf0e,0xbf80bf62bf048000,0x3f183dc9bedbbf55,0x3eac3f463f7d3f6d,0xbf78bf75bf2cbe48,
0xbf65bf043cc93f0e,0x3e60beacbf4abf7f,0xbe89bf3ebf7cbf6d,0x3f6a3f7d3f423e95,0x3f7f3f4e3eb8be48,0xbf13bd493efc3f62,0xbdfb3edb3f583f80,0xbf31bf78bf73bf22,
0xbee6bf5cbf80bf55,0x3f7a3f713f1d3dc9,0x3f773f2c3e2fbec4,0xbecf3e163f273f75,0x3d973f183f6f3f7b,0xbf51bf80bf5fbef1,0xbf7ebf67bf098000,0x3f393e79bea1bf46,
0xbe483ec43f553f80,0xbf0ebf6dbf7bbf35,0x3f7b3f6d3f0e0000,0xbf55bec43e483f35,0x3e48bec4bf55bf80,0x3f0e3f6d3f7b3f35,0xbf7bbf6dbf0e0000,0x3f553ec4be48bf35,
0xbf7bbf6dbf0e8000,0x3f553ec4be48bf35,0xbe483ec43f553f80,0xbf0ebf6dbf7bbf35,0x3f7b3f6d3f0e8000,0xbf55bec43e483f35,0x3e48bec4bf55bf80,0x3f0e3f6d3f7b3f35,
0x3f653f7d3f393e48,0xbf7abf2cbdfb3ef1,0xbe893eac3f513f80,0xbecfbf5cbf7fbf46,0xbf27bf78bf6fbf0e,0x3f7c3f673efcbdc9,0x3f1d3d49bf09bf6d,0x3cc93f183f733f75,
0xbee63e163f313f7b,0xbe60bf3ebf7ebf62,0xbf77bf71bf138000,0x3f6a3f04bd97bf22,0x3f423e79beb8bf55,0xbe2f3edb3f5f3f7f,0x3f4a3f803f583ec4,0xbf80bf4ebea13e95,
0x3f673ef1be16bf35,0xbf043dc93f2c3f7b,0xbd49bf22bf78bf6d,0x3f183f753f713f0e,0xbeac3e953f4e3f80,0xbe79bf46bf80bf55,0x3f3e3f7f3f5c3ec4,0xbf7dbf62bedb3e48,
0x3edb3f623f7d3f35,0xbf5cbf7fbf3ebe48,0x3f803f463e79bec4,0xbf4ebe953eac3f55,0xbf71bf75bf188000,0x3f783f223d49bf0e,0xbf2cbdc93f043f6d,0x3e16bef1bf67bf7b,
0x3f13bd49bf27bf7b,0xbdfb3f043f6f3f75,0x3f803f4e3e89bec4,0xbf65bedb3e603f46,0x3f093f713f733f0e,0xbf5fbf7dbf31bdc9,0xbecf3e793f4a3f80,0xbd97bf2cbf7cbf62,
0x3f513f803f423e48,0xbf7ebf5cbeb83e95,0xbcc93f183f773f6d,0xbee6bf67bf7abf22,0xbf58beac3ea13f55,0x3efcbe16bf39bf7f,0xbf6abf78bf1d8000,0x3f7f3f3e3e2fbef1,
0xbef13e483f463f80,0x3dc9bf0ebf75bf6d,0x3e953f553f7f3f35,0xbf22bf7bbf62bec4,0x3f623f7b3f220000,0xbf7fbf55be953ec4,0x3f753f0ebdc9bf35,0xbf46be483ef13f6d,
0xbf62bf7bbf228000,0x3f7f3f553e95bec4,0xbf75bf0e3dc93f35,0x3f463e48bef1bf6d,0xbef13e483f463f80,0x3dc9bf0ebf75bf6d,0x3e953f553f7f3f35,0xbf22bf7bbf62bec4,
0x3cc93f2c3f7e3f55,0xbea1bf5cbf7cbf22,0xbf093e163f423f80,0x3e89bedbbf6abf75,0x3f6f3f713efcbe48,0xbf7fbf4ebe603ef1,0x3f133f783f653ec4,0xbf4abf80bf39bdc9,
0xbf80bf3ebdfb3f0e,0x3f733f04be2fbf46,0xbf58bf7dbf278000,0x3f773f673ecfbe95,0xbeb83eac3f5f3f7b,0x3d97bf18bf7abf62,0xbf51be793ee63f6d,0x3f1dbd49bf31bf7f,
0x3e163f463f803f35,0xbeacbf62bf78bf0e,0x3f043f753f673ec4,0xbf2cbf7fbf4ebe48,0xbf183dc93f3e3f80,0x3edbbe95bf5cbf7b,0xbe793ef13f713f6d,0x3d49bf22bf7dbf55,
0xbf7dbf223d493f35,0x3f713ef1be79bf55,0xbf5cbe953edb3f6d,0x3f3e3dc9bf18bf7b,0xbf4ebf7fbf2c8000,0x3f673f753f04be48,0xbf78bf62beac3ec4,0x3f803f463e16bf0e,
0xbdfb3f183f7c3f55,0x3cc9bf2cbf7fbf46,0xbea13edb3f6f3f6d,0x3e60bf04bf77bf62,0xbefc3e793f583f7b,0x3ecfbeacbf65bf75,0xbf273d493f393f80,0x3f13be16bf4abf7f,
0xbf7ebf4ebe2f3f0e,0x3f803f3e3d97bf22,0xbf73bf67beb83ec4,0x3f7a3f5c3e89bef1,0xbf5fbf78bf093e48,0x3f6a3f713ee6be95,0xbf42bf80bf318000,0x3f513f7d3f1dbdc9,
0x3f003f003f003f00,0x3f003f003f003f00,0x3f003f003f003f00,0x3f003f003f003f00,0x3f003f003f003f00,0x3f003f003f003f00,0x3f003f003f003f00,0x3f003f003f003f00,
0xbf003f00bf003f00,0xbf003f00bf003f00,0xbf003f00bf003f00,0xbf003f00bf003f00,0xbf003f00bf003f00,0xbf003f00bf003f00,0xbf003f00bf003f00,0xbf003f00bf003f00,
0x3efc3f043f093f0e,0x3ecf3edb3ee63ef1,0x3f273f2c3f313f35,0x3f133f183f1d3f22,0x3dfb3e163e2f3e48,0x3cc93d493d973dc9,0x3ea13eac3eb83ec4,0x3e603e793e893e95,
0xbf5fbf5cbf58bf55,0xbf6abf67bf65bf62,0xbf42bf3ebf39bf35,0xbf51bf4ebf4abf46,0xbf7ebf7dbf7cbf7b,0xbf80bf80bf7fbf7f,0xbf73bf71bf6fbf6d,0xbf7abf78bf77bf75,
0xbf4ebf46bf3ebf35,0xbf67bf62bf5cbf55,0xbf78bf75bf71bf6d,0xbf80bf7fbf7dbf7b,0xbe16bdc9bd490000,0xbeacbe95be79be48,0xbf04bef1bedbbec4,0xbf2cbf22bf18bf0e,
0xbf18bf22bf2cbf35,0xbedbbef1bf04bf0e,0xbe79be95beacbec4,0xbd49bdc9be16be48,0xbf7dbf7fbf80bf80,0xbf71bf75bf78bf7b,0xbf5cbf62bf67bf6d,0xbf3ebf46bf4ebf55,
0xbeb8bedbbefcbf0e,0xbd97be16be60be95,0xbf51bf5cbf65bf6d,0xbf1dbf2cbf39bf46,0xbf80bf80bf7ebf7b,0xbf73bf78bf7cbf7f,0xbf58bf4ebf42bf35,0xbf77bf71bf6abf62,
0x3f6f3f673f5f3f55,0x3f7f3f7d3f7a3f75,0x3f133f043ee63ec4,0x3f4a3f3e3f313f22,0x3cc9bd49bdfbbe48,0x3ea13e793e2f3dc9,0xbf09bf18bf27bf35,0xbe89beacbecfbef1,
0xbf75bf7bbf7fbf80,0xbf46bf55bf62bf6d,0xbef1bf0ebf22bf35,0xbdc9be48be95bec4,0x3e953e483dc90000,0x3f223f0e3ef13ec4,0x3f623f553f463f35,0x3f7f3f7b3f753f6d,
0x3e953e483dc98000,0x3f223f0e3ef13ec4,0x3f623f553f463f35,0x3f7f3f7b3f753f6d,0x3f753f7b3f7f3f80,0x3f463f553f623f6d,0x3ef13f0e3f223f35,0x3dc93e483e953ec4,
0x3f093edb3ea13e48,0x3f5f3f4e3f393f22,0xbecfbf04bf1dbf35,0x3d97bd49be2fbe95,0x3f133f2c3f423f55,0x3dfb3e793eb83ef1,0x3f803f7d3f773f6d,0x3f653f713f7a3f7f,
0x3f583f673f733f7b,0x3efc3f183f313f46,0x3f6a3f5c3f4a3f35,0x3f7f3f803f7c3f75,0xbf51bf3ebf27bf0e,0xbf7ebf78bf6fbf62,0x3cc93e163e893ec4,0xbee6beacbe60bdc9,
0x3eac3ef13f183f35,0xbe79bdc93d493e48,0xbf3ebf22bf04bec4,0xbf7dbf75bf67bf55,0x3edb3e953e160000,0x3f5c3f463f2c3f0e,0x3f803f7f3f783f6d,0x3f4e3f623f713f7b,
0xbf71bf62bf4ebf35,0xbf78bf7fbf80bf7b,0xbf2cbf46bf5cbf6d,0xbe16be95bedbbf0e,0x3f673f753f7d3f80,0x3f043f223f3e3f55,0xbd493dc93e793ec4,0xbf18bef1beacbe48,
0xbf42bf5cbf6fbf7b,0xbe2fbeacbefcbf22,0xbf4abf2cbf09bec4,0xbf80bf7dbf73bf62,0x3ee63f183f393f55,0xbe60bd493dfb3e95,0x3f773f673f513f35,0x3f6a3f783f7f3f7f,
0x3f273f043eb83e48,0x3f7c3f713f5f3f46,0xbf1dbf3ebf58bf6d,0x3cc9be16bea1bef1,0xbf65bf4ebf31bf0e,0xbf7abf80bf7ebf75,0x3e893edb3f133f35,0xbecfbe79bd973dc9,
0x3f553f6d3f7b3f80,0x3e483ec43f0e3f35,0xbf0ebec4be480000,0xbf7bbf6dbf55bf35,0xbf55bf6dbf7bbf80,0xbe48bec4bf0ebf35,0x3f0e3ec43e480000,0x3f7b3f6d3f553f35,
0xbf0ebec4be488000,0xbf7bbf6dbf55bf35,0xbf55bf6dbf7bbf80,0xbe48bec4bf0ebf35,0x3f0e3ec43e488000,0x3f7b3f6d3f553f35,0x3f553f6d3f7b3f80,0x3e483ec43f0e3f35,
0xbf7fbf7dbf6fbf55,0xbf13bf3ebf5fbf75,0x3dfb3eac3f093f35,0xbf31bf04bea1bdc9,0x3f653f783f803f7b,0x3e603edb3f1d3f46,0x3e893d49be2fbec4,0x3f6a3f4e3f273ef1,
0x3d97be16beb8bf0e,0x3f513f2c3efc3e95,0xbf7ebf71bf58bf35,0xbf39bf5cbf73bf7f,0xbee6be79bcc93e48,0xbf7abf67bf4abf22,0x3f773f803f7c3f6d,0x3ecf3f183f423f62,
0x3f803f753f5c3f35,0x3f183f463f673f7b,0xbeacbdc93e163ec4,0xbf78bf62bf3ebf0e,0xbf2cbef1be790000,0xbf7dbf7fbf71bf55,0xbedbbf22bf4ebf6d,0x3f043e953d49be48,
0x3d493e953f043f35,0xbf4ebf22bedbbe48,0xbf71bf7fbf7dbf6d,0xbe79bef1bf2cbf55,0xbf3ebf62bf78bf80,0x3e16bdc9beacbf0e,0x3f673f463f183ec4,0x3f5c3f753f803f7b,
0xbf7abf80bf73bf55,0xbe89bf04bf39bf62,0x3eb83f183f4a3f6d,0xbf27bedbbe2f3dc9,0x3f133eac3d97be48,0x3f7e3f7d3f6a3f46,0xbf80bf78bf5fbf35,0xbee6bf2cbf58bf75,
0x3e60bd49bea1bf0e,0x3f773f5c3f313ef1,0xbf6fbf4ebf1dbec4,0xbf42bf67bf7cbf7f,0x3f513f713f7f3f7b,0xbdfb3e163ecf3f22,0x3cc9be79befcbf35,0x3f653f3e3f093e95,
0xbf22bf55bf75bf80,0x3ef13e48bdc9bec4,0x3f7f3f7b3f623f35,0x3e953f0e3f463f6d,0xbf46bf0ebe950000,0xbf62bf7bbf7fbf6d,0x3dc9be48bef1bf35,0x3f753f553f223ec4,
0x3f463f0e3e958000,0x3f623f7b3f7f3f6d,0xbdc93e483ef13f35,0xbf75bf55bf22bec4,0xbf22bf55bf75bf80,0x3ef13e48bdc9bec4,0x3f7f3f7b3f623f35,0x3e953f0e3f463f6d,
0x3ecf3f2c3f5f3f7b,0xbf42bf04be603dc9,0x3e2fbe16bee6bf35,0x3f7e3f673f393ef1,0x3f803f713f4a3f0e,0x3ea13f183f513f75,0xbf58bf78bf7fbf6d,0x3e89bd49beb8bf22,
0xbf6abf3ebefcbe48,0xbf27bf5cbf7abf7f,0x3f7c3f7d3f653f35,0x3dfb3edb3f313f62,0x3cc93eac3f1d3f55,0xbf73bf4ebf13be95,0x3f093e79bd97bec4,0x3f773f803f6f3f46,
0x3e79bdc9bedbbf35,0x3f803f753f4e3f0e,0x3e163ef13f3e3f6d,0xbf71bf46bf04be48,0x3f5c3f223eac0000,0x3f2c3f623f7d3f7b,0xbf18be953d493ec4,0xbf67bf7fbf78bf55,
0x3f783f7f3f673f35,0xbd493e953f183f55,0xbf7dbf62bf2cbec4,0xbeacbf22bf5cbf7b,0x3f043f463f713f80,0xbf3ebef1be163e48,0xbf4ebf75bf80bf6d,0x3edb3dc9be79bf0e,
0xbf77bf4ebf09be48,0xbeb8bf2cbf65bf7f,0x3f7f3f673f313ec4,0x3e2f3f043f4a3f75,0xbf7ebf78bf51bf0e,0x3cc9beacbf27bf62,0x3f733f803f6a3f35,0xbe603e163efc3f46,
0xbe89bf18bf58bf7b,0x3f6f3f3e3ee63dc9,0x3d973edb3f393f6d,0xbf7cbf5cbf1dbe95,0x3dfbbe79bf13bf55,0x3f803f713f423ef1,0xbea13d493ecf3f35,0xbf7abf7dbf5fbf22,
0x3ec43f353f6d3f80,0xbf6dbf35bec40000,0xbec4bf35bf6dbf80,0x3f6d3f353ec40000,0x3ec43f353f6d3f80,0xbf6dbf35bec40000,0xbec4bf35bf6dbf80,0x3f6d3f353ec40000,
0xbf6dbf35bec48000,0xbec4bf35bf6dbf80,0x3f6d3f353ec48000,0x3ec43f353f6d3f80,0xbf6dbf35bec48000,0xbec4bf35bf6dbf80,0x3f6d3f353ec48000,0x3ec43f353f6d3f80,
0x3f1d3e79be2fbf0e,0x3f393f713f7f3f62,0xbee6bd493eb83f35,0xbf58bf7dbf77bf46,0x3f5f3f183e60be48,0x3ecf3f3e3f733f7f,0xbf42bedbbcc93ec4,0xbf13bf5cbf7ebf75,
0x3f4a3f783f7c3f55,0xbf31beac3d973ef1,0xbf65bf80bf6fbf35,0x3f093e16be89bf22,0x3efc3f4e3f7a3f7b,0xbf6abf2cbea13dc9,0xbf27bf67bf80bf6d,0x3f513f043dfbbe95,
0xbf5cbf7fbf71bf35,0x3f2c3e95be16bf0e,0x3f183f623f803f6d,0xbf67bf22be793e48,0xbf78bf46bedb0000,0xbd49bef1bf4ebf7b,0x3f7d3f753f3e3ec4,0xbeac3dc93f043f55,
0x3f043dc9beacbf35,0x3f3e3f753f7d3f55,0xbf4ebef1bd493ec4,0xbedbbf46bf78bf7b,0xbe79bf22bf67bf80,0x3f803f623f183e48,0xbe163e953f2c3f6d,0xbf71bf7fbf5cbf0e,
0xbf39beac3dfb3f0e,0xbee6bf4ebf7cbf75,0x3e60be79bf27bf6d,0x3f5f3f803f6a3f22,0x3eb83f3e3f773f7b,0xbf7fbf5cbf09bdc9,0xbf51bf7dbf73bf35,0x3f4a3edbbcc9bef1,
0xbf31bf71bf7ebf55,0x3f653f183e2fbe95,0x3f7a3f783f423ec4,0xbefcbd493ecf3f46,0xbf6fbf2cbe893e48,0xbd97bf04bf58bf7f,0x3f133e16bea1bf35,0x3f1d3f673f803f62,
0xbdc9bf0ebf62bf80,0x3f753f7b3f463ec4,0xbf22be483e953f35,0xbef1bf55bf7fbf6d,0x3f7f3f553ef10000,0xbe953e483f223f6d,0xbf46bf7bbf75bf35,0x3f623f0e3dc9bec4,
0x3f7f3f553ef18000,0xbe953e483f223f6d,0xbf46bf7bbf75bf35,0x3f623f0e3dc9bec4,0x3dc93f0e3f623f80,0xbf75bf7bbf46bec4,0x3f223e48be95bf35,0x3ef13f553f7f3f6d,
0xbf7cbf71bf27be48,0x3f1d3e16beb8bf46,0x3f313e79be89bf35,0x3ea13f3e3f7a3f75,0x3f093d49bee6bf55,0x3efc3f5c3f803f62,0x3ecf3f4e3f7e3f6d,0xbf7fbf67bf13bdc9,
0x3e2fbeacbf42bf7b,0x3f4a3f7d3f6f3f22,0x3f393f783f773f35,0xbf73bf2cbe603e95,0x3f583f803f653f0e,0xbf5fbf04bcc93ef1,0xbf6abf18bdfb3ec4,0x3d97bedbbf51bf7f,
0xbf3ebe953e793f35,0xbe16bf22bf71bf7b,0x3f673f7f3f4e3ec4,0xbf5cbef13d493f0e,0x3f803f623f040000,0xbf18bdc93edb3f55,0xbeacbf46bf7dbf6d,0x3f783f753f2c3e48,
0xbf2cbf75bf78bf35,0x3f7d3f463eacbe48,0xbedb3dc93f183f6d,0xbf04bf62bf80bf55,0xbd493ef13f5c3f80,0xbf4ebf7fbf67bf0e,0x3f713f223e16bec4,0xbe793e953f3e3f7b,
0xbea13e793f393f7b,0xbf09bf67bf7ebf46,0xbf5fbf80bf51bec4,0x3f6f3f183d97bef1,0x3f273e16becfbf55,0x3e2f3f2c3f773f75,0x3f1d3f713f7a3f35,0xbf80bf5cbee63dc9,
0xbf73bf78bf31be48,0x3f583edbbdfbbf22,0x3efcbd49bf13bf6d,0x3eb83f4e3f7f3f62,0x3f423f7d3f6a3f0e,0xbf7cbf3ebe893e95,0xbf4abeac3e603f35,0x3cc9bf04bf65bf7f,
0xbe483ec43f553f80,0xbf0ebf6dbf7bbf35,0x3f7b3f6d3f0e0000,0xbf55bec43e483f35,0x3e48bec4bf55bf80,0x3f0e3f6d3f7b3f35,0xbf7bbf6dbf0e0000,0x3f553ec4be48bf35,
0xbf7bbf6dbf0e8000,0x3f553ec4be48bf35,0xbe483ec43f553f80,0xbf0ebf6dbf7bbf35,0x3f7b3f6d3f0e8000,0xbf55bec43e483f35,0x3e48bec4bf55bf80,0x3f0e3f6d3f7b3f35,
0x3ea13f4e3f803f55,0xbf58bf80bf4abe95,0xbf5fbedb3e2f3f35,0x3eb8be79bf42bf7f,0x3d97bf04bf6abf7b,0x3f133f713f773f22,0x3f7e3f3e3e60bec4,0xbf31be163ee63f62,
0xbf73bf18bcc93f0e,0x3f09bd49bf1dbf75,0xbefcbf67bf7cbf35,0x3f6f3f783f273dc9,0x3f7f3f5c3ecfbe48,0xbf51beac3e893f46,0x3dfb3f2c3f7a3f6d,0xbf39bf7dbf65bef1,
0x3edb3f623f7d3f35,0xbf5cbf7fbf3ebe48,0x3f803f463e79bec4,0xbf4ebe953eac3f55,0xbf71bf75bf180000,0x3f783f223d49bf0e,0xbf2cbdc93f043f6d,0x3e16bef1bf67bf7b,
0xbf67bef13e163f35,0x3f04bdc9bf2cbf7b,0x3d493f223f783f6d,0xbf18bf75bf71bf0e,0x3eacbe95bf4ebf80,0x3e793f463f803f55,0xbf3ebf7fbf5cbec4,0x3f7d3f623edbbe48,
0x3e2f3f3e3f7f3f55,0xbf1dbf78bf6abef1,0xbf39be163efc3f6d,0x3ea1beacbf58bf7f,0xbf7abf67bee63e48,0x3f773f18bcc9bf22,0xbeb8bf5cbf7ebf35,0x3f423f803f513e95,
0xbf7cbf2cbd973f0e,0x3f4a3e79becfbf62,0xbf31bf7dbf5fbec4,0x3f733f713f09bdc9,0x3e60bedbbf65bf7b,0x3e893f4e3f803f46,0x3f6f3f04bdfbbf35,0xbf27bd493f133f75,
0x3ef1be48bf46bf80,0xbdc93f0e3f753f6d,0xbe95bf55bf7fbf35,0x3f223f7b3f623ec4,0xbf62bf7bbf220000,0x3f7f3f553e95bec4,0xbf75bf0e3dc93f35,0x3f463e48bef1bf6d,
0x3f623f7b3f228000,0xbf7fbf55be953ec4,0x3f753f0ebdc9bf35,0xbf46be483ef13f6d,0x3ef1be48bf46bf80,0xbdc93f0e3f753f6d,0xbe95bf55bf7fbf35,0x3f223f7b3f623ec4,
0x3f313d49bf1dbf7b,0xbee63e793f513f7f,0x3f7a3f18bd97bf35,0xbf5fbeac3eb83f62,0xbecfbf67bf77bf0e,0x3f273f7d3f583e95,0x3e2fbf04bf73bf6d,0x3dfb3f3e3f803f46,
0x3f393f803f4a3e48,0xbf65bf78bf133dc9,0x3e603f4e3f7f3f35,0xbefcbf71bf6fbef1,0x3f6a3edbbe89bf55,0xbf42be163f093f75,0x3f7c3f5c3ea1bec4,0xbf7ebf2cbcc93f22,
0x3f7d3f22bd49bf35,0xbf71bef13e793f55,0x3f5c3e95bedbbf6d,0xbf3ebdc93f183f7b,0x3f4e3f7f3f2c0000,0xbf67bf75bf043e48,0x3f783f623eacbec4,0xbf80bf46be163f0e,
0x3e163f463f803f35,0xbeacbf62bf78bf0e,0x3f043f753f673ec4,0xbf2cbf7fbf4ebe48,0xbf183dc93f3e3f80,0x3edbbe95bf5cbf7b,0xbe793ef13f713f6d,0x3d49bf22bf7dbf55,
0x3f1d3f7d3f513e48,0xbf31bf80bf42bdc9,0x3ee63f713f6a3ec4,0xbf09bf78bf5fbe95,0x3e893f5c3f7a3f0e,0xbeb8bf67bf73bef1,0x3d973f3e3f803f35,0xbe2fbf4ebf7ebf22,
0xbf4abe163f133f7b,0x3f393d49bf27bf7f,0xbf65beac3ecf3f6d,0x3f583e79befcbf75,0xbf77bf043e603f55,0x3f6f3edbbea1bf62,0xbf7fbf2c3cc93f35,0x3f7c3f18bdfbbf46,
0xbf8000003f80,0xbf8000003f80,0xbf8000003f80,0xbf8000003f80,0xbf8000003f80,0xbf8000003f80,0xbf8000003f80,0xbf8000003f80,
0x3f808000bf808000,0x3f808000bf808000,0x3f808000bf808000,0x3f808000bf808000,0x3f808000bf808000,0x3f808000bf808000,0x3f808000bf808000,0x3f808000bf808000,
0x3e89bf78be603f7b,0x3eb8bf71bea13f75,0x3d97bf80bcc93f80,0x3e2fbf7dbdfb3f7f,0x3f1dbf4ebf133f55,0x3f31bf3ebf273f46,0x3ee6bf67becf3f6d,0x3f09bf5cbefc3f62,
0x3f773e79bf7abe48,0x3f6f3eacbf73be95,0x3f7f3d49bf808000,0x3f7c3e16bf7ebdc9,0x3f4a3f18bf51bf0e,0x3f393f2cbf42bf22,0x3f653edbbf6abec4,0x3f583f04bf5fbef1,
0x3f4ebf22bf3e3f35,0x3f67bef1bf5c3f0e,0x3f78be95bf713ec4,0x3f80bdc9bf7d3e48,0x3e16bf7fbd493f80,0x3eacbf75be793f7b,0x3f04bf62bedb3f6d,0x3f2cbf46bf183f55,
0x3f183f46bf2cbf35,0x3edb3f62bf04bf55,0x3e793f75beacbf6d,0x3d493f7fbe16bf7b,0x3f7d3dc9bf808000,0x3f713e95bf78be48,0x3f5c3ef1bf67bec4,0x3f3e3f22bf4ebf0e,
0x3f6a3eacbf77be48,0x3f423f18bf58bef1,0x3f7cbe79bf733ec4,0x3f7e3d49bf803dc9,0x3f39bf3ebf1d3f55,0x3f65bf04bf513f22,0x3e60bf7dbd973f80,0x3efcbf67beb83f75,
0xbecf3f713e89bf7b,0xbf273f4e3f09bf62,0x3e2f3f78bea1bf6d,0xbdfb3f80bcc9bf7f,0x3f313f2cbf4abf0e,0x3ee63f5cbf13bf46,0x3f7a3e16bf7f8000,0x3f5f3edbbf6fbe95,
0x3e95bf7bbdc93f80,0x3f22bf55bef13f6d,0x3f62bf0ebf463f35,0x3f7fbe48bf753ec4,0x3f753e48bf7f0000,0x3f463f0ebf62bec4,0x3ef13f55bf22bf35,0x3dc93f7bbe95bf6d,
0x3f753e48bf7f8000,0x3f463f0ebf62bec4,0x3ef13f55bf22bf35,0x3dc93f7bbe95bf6d,0xbe953f7b3dc9bf80,0xbf223f553ef1bf6d,0xbf623f0e3f46bf35,0xbf7f3e483f75bec4,
0x3f7abeacbf653f0e,0x3f773e16bf803dc9,0x3eb8bf78bdfb3f80,0x3f42bf3ebf133f62,0xbe2f3f80bd97bf7b,0xbf1d3f5c3ecfbf75,0x3f393f18bf5fbec4,0x3ea13f67bf09bf46,
0x3e603f71bee6bf55,0xbe893f7d3cc9bf7f,0x3f6f3e79bf7e8000,0x3f273f2cbf51bef1,0xbf7cbd493f7fbe48,0xbf4abf043f6a3e95,0xbf313f4e3efcbf6d,0xbf733edb3f58bf22,
0x3eac3f62bf18bf35,0xbe793f7fbd49bf7b,0xbf3e3f463f04bf6d,0xbf7d3e953f67bf0e,0x3edbbf75be163f80,0x3f5cbf22bf2c3f55,0x3f80bdc9bf783ec4,0x3f4e3ef1bf71be48,
0xbf713ef13f4ebf35,0xbf78bdc93f80be48,0xbf2cbf223f5c3ec4,0xbe16bf753edb3f55,0x3f673e95bf7d8000,0x3f043f46bf3ebf0e,0xbd493f7fbe79bf6d,0xbf183f623eacbf7b,
0xbf7f3e793f6abf0e,0xbf51bedb3f773dc9,0xbdfb3f80be60bf6d,0xbf393f4e3ee6bf75,0x3f733e16bf803e48,0x3f093f3ebf4abef1,0x3efcbf71be2f3f80,0x3f6fbf04bf423f46,
0xbd97bf783ecf3f55,0x3f13bf67be893f7f,0xbf7e3d493f7abec4,0xbf31bf183f653e95,0xbea13f7dbcc9bf7b,0xbf583f2c3f1dbf62,0x3f5f3eacbf7c8000,0x3eb83f5cbf27bf22,
0x3f0ebf6dbe483f80,0x3f7bbec4bf553f35,0x3f553ec4bf7b0000,0x3e483f6dbf0ebf35,0xbf0e3f6d3e48bf80,0xbf7b3ec43f55bf35,0xbf55bec43f7b0000,0xbe48bf6d3f0e3f35,
0x3f553ec4bf7b8000,0x3e483f6dbf0ebf35,0xbf0e3f6d3e48bf80,0xbf7b3ec43f55bf35,0xbf55bec43f7b8000,0xbe48bf6d3f0e3f35,0x3f0ebf6dbe483f80,0x3f7bbec4bf553f35,
0x3f273f18bf6abe48,0xbe2f3f80be89bf62,0x3f1dbf67be603f80,0x3f80be79bf653f22,0xbea1bf5c3f313f0e,0x3f09bf71bdfb3f7f,0xbf5f3f2c3f13bf6d,0xbf6fbe163f7fbe95,
0xbf423f4e3ecfbf7b,0xbf7c3d493f77bef1,0x3f4a3edbbf7a8000,0x3cc93f78bee6bf46,0x3f73bf04bf393f55,0x3f583eacbf7e3dc9,0xbefcbf3e3f513ec4,0x3eb8bf7d3d973f75,
0xbf803e953f5cbf35,0xbf18bf223f673e48,0x3eacbf7f3e163f6d,0x3f78bef1bf3e3f55,0x3f2cbf62be793f80,0x3f7dbdc9bf713f0e,0x3edb3f46bf4ebec4,0xbf043f753d49bf7b,
0xbd49bf753f043f35,0x3f4ebf46bedb3f7b,0x3f713dc9bf7d3ec4,0x3e793f62bf2cbf0e,0x3f3e3ef1bf788000,0xbe163f7fbeacbf55,0xbf673f223f18bf6d,0xbf5cbe953f80be48,
0x3f58bf3ebee63f7b,0x3f5f3e79bf803e95,0xbf6abe163f7ebec4,0xbd97bf713f133f22,0x3e2f3f67bf27bf0e,0xbf4a3f4e3eb8bf7f,0x3f39bf5cbe893f80,0x3f733d49bf7a3ef1,
0x3f093f2cbf65be48,0xbefc3f78bcc9bf75,0x3ecfbf7d3dfb3f6d,0x3f7fbeacbf513f46,0xbf7c3edb3f42bf55,0xbf1dbf183f6f3dc9,0x3f313f04bf778000,0xbea13f80be60bf62,
0x3f46bf55be953f80,0x3f623e48bf7f3ec4,0xbdc93f7bbef1bf35,0xbf753f0e3f22bf6d,0xbf22bf0e3f750000,0x3ef1bf7b3dc93f6d,0x3f7fbe48bf623f35,0x3e953f55bf46bec4,
0x3f223f0ebf758000,0xbef13f7bbdc9bf6d,0xbf7f3e483f62bf35,0xbe95bf553f463ec4,0x3f46bf55be953f80,0x3f623e48bf7f3ec4,0xbdc93f7bbef1bf35,0xbf753f0e3f22bf6d,
0xbeb83f80be89bf55,0xbf7f3e793f58bf46,0x3f51bf4ebea13f80,0x3f4a3eacbf803e95,0x3f393edbbf7e3e48,0xbee63f7dbe2fbf62,0xbe60bf5c3f423ec4,0x3f5fbf3ebecf3f7f,
0xbf6fbd493f77bf0e,0x3d97bf783f093f22,0x3f133f18bf738000,0xbf1d3f713cc9bf75,0xbf313f673dfbbf7b,0xbf65be163f7cbef1,0x3f7abf04bf273f6d,0x3efc3f2cbf6abdc9,
0x3e79bf7f3edb3f35,0x3f80be95bf4e3f55,0x3e163f62bf3ebec4,0xbf713f223f04bf7b,0x3f5cbf46beac3f80,0x3f2c3ef1bf7d3e48,0xbf183f75bd49bf6d,0xbf67bdc93f78bf0e,
0x3f78bdc9bf673f35,0xbd493f75bf18bf0e,0xbf7d3ef13f2cbf6d,0xbeacbf463f5c3e48,0x3f043f22bf718000,0xbf3e3f623e16bf7b,0xbf4ebe953f80bec4,0x3edbbf7f3e793f55,
0xbefc3f7dbe60bf55,0xbf6abd493f73bf22,0x3f27bf713cc93f6d,0x3f513e79bf7e3ef1,0xbf4a3f5c3e2fbf7b,0xbf31bedb3f7fbe95,0x3f65bf3ebeb83f80,0x3f093f18bf773dc9,
0xbf5fbe163f7abf0e,0x3ecfbf803ea13f46,0x3f423eacbf803ec4,0xbf133f78bdfbbf62,0xbf1dbf043f7cbe48,0x3f39bf67bd973f75,0x3ee63f2cbf6f8000,0xbf583f4e3e89bf7f,
0x3f6dbf35bec43f80,0x3ec43f35bf6d0000,0xbf6d3f353ec4bf80,0xbec4bf353f6d0000,0x3f6dbf35bec43f80,0x3ec43f35bf6d0000,0xbf6d3f353ec4bf80,0xbec4bf353f6d0000,
0x3ec43f35bf6d8000,0xbf6d3f353ec4bf80,0xbec4bf353f6d8000,0x3f6dbf35bec43f80,0x3ec43f35bf6d8000,0xbf6d3f353ec4bf80,0xbec4bf353f6d8000,0x3f6dbf35bec43f80,
0xbf7e3f043f13bf7b,0xbcc9bf673f423e95,0x3f73bf2cbecf3f80,0x3e603f4ebf5fbdc9,0xbf773e163f58bf55,0x3eb8bf803ee63f22,0x3f7fbeacbf393f6d,0xbe2f3f78bf1dbef1,
0xbdfbbf5c3f513e48,0x3f80bedbbf273f75,0x3ea13f3ebf6a8000,0xbf7a3f183efcbf7f,0x3e89bf7d3f093f0e,0x3f6fbd49bf653f46,0xbd973f71bf31bec4,0xbf7c3e793f4abf62,
0x3f5c3dc9bf713f35,0xbf2c3f75be16bf55,0xbf18bef13f80bec4,0x3f67bf46be793f7b,0x3f78bf22bedb3f80,0x3d493f62bf4ebe48,0xbf7d3e953f3ebf6d,0x3eacbf7f3f043f0e,
0xbf043f7fbeacbf35,0xbf3ebe953f7dbf0e,0x3f4ebf62bd493f6d,0x3edb3f22bf783e48,0x3e793f46bf678000,0xbf803ef13f18bf7b,0x3e16bf753f2c3ec4,0x3f71bdc9bf5c3f55,
0x3cc9bf673f4a3e48,0x3f73be16bf513f62,0x3f093f04bf7f3ec4,0xbf773f2c3eb8bf7f,0xbf6a3d493f5fbf55,0x3f27bf783e603f46,0x3f7cbf18bee63f80,0xbdfb3f71bf39be95,
0x3f80bedbbf1d3f7b,0xbea13f7dbf13bef1,0xbf583f5c3d97bf6d,0xbe89bf3e3f6fbdc9,0x3ecfbf803efc3f0e,0x3f423e79bf7a3f22,0x3e2f3f4ebf658000,0xbf7e3eac3f31bf75,
0x3f7fbf0ebef13f80,0xbe953f7bbf22bec4,0xbf46be483f75bf35,0x3f62bf55bdc93f6d,0x3dc93f55bf620000,0xbf753e483f46bf6d,0x3f22bf7b3e953f35,0x3ef13f0ebf7f3ec4,
0x3dc93f55bf628000,0xbf753e483f46bf6d,0x3f22bf7b3e953f35,0x3ef13f0ebf7f3ec4,0xbf7f3f0e3ef1bf80,0x3e95bf7b3f223ec4,0x3f463e48bf753f35,0xbf623f553dc9bf6d,
0xbf13bedb3f7fbf0e,0x3f7ebf18becf3f7f,0x3f80bf04befc3f80,0xbee63f80bf09bef1,0x3f7abf2cbea13f7b,0xbe893f78bf31be95,0xbeb83f7dbf1dbec4,0xbf27beac3f7cbf22,
0x3f51bf673d973f55,0x3dfb3f4ebf6a3dc9,0x3cc93f5cbf5f8000,0xbf653d493f58bf62,0x3e603f3ebf733e48,0xbf773e793f39bf75,0xbf6f3e163f4abf6d,0x3f42bf713e2f3f46,
0xbf3e3f75be79bf35,0xbe16bf463f71be48,0x3f67bdc9bf4e3f6d,0xbf5c3f62bd49bf55,0x3f80bef1bf043f80,0xbf183f7fbedbbf0e,0xbeacbf223f7dbec4,0x3f78be95bf2c3f7b,
0xbf2cbe953f78bf35,0x3f7dbf22beac3f7b,0xbedb3f7fbf18bec4,0xbf04bef13f80bf0e,0xbd493f62bf5c8000,0xbf4ebdc93f67bf55,0x3f71bf46be163f6d,0xbe793f75bf3ebe48,
0x3ee63f04bf803f0e,0xbf7a3eac3f1dbf7f,0xbf773f3e3e2fbf6d,0x3ecfbf7d3f273e95,0xbd97bf4e3f6fbe48,0x3f513d49bf5f3f62,0x3f7ebedbbf093f80,0xbf393f78bea1bf22,
0xbf653f5cbcc9bf55,0x3e60bf713f4a3dc9,0xbe89bf2c3f7cbec4,0x3f6abe16bf423f75,0x3f7fbf18beb83f7b,0xbf133f80befcbef1,0xbdfb3f67bf588000,0xbf31be793f73bf46,
0x3f7bbec4bf0e3f80,0xbf553f6dbe48bf35,0x3e48bf6d3f550000,0x3f0e3ec4bf7b3f35,0xbf7b3ec43f0ebf80,0x3f55bf6d3e483f35,0xbe483f6dbf550000,0xbf0ebec43f7bbf35,
0xbe483f6dbf558000,0xbf0ebec43f7bbf35,0x3f7bbec4bf0e3f80,0xbf553f6dbe48bf35,0x3e48bf6d3f558000,0x3f0e3ec4bf7b3f35,0xbf7b3ec43f0ebf80,0x3f55bf6d3e483f35,
0x3ee6bf7d3f313e48,0x3e603f2cbf7e3ef1,0x3f77beacbf133f80,0xbf6a3f5cbd97bf46,0xbf423f78beb8bf0e,0x3e2fbf673f5fbdc9,0xbf4abd493f58bf6d,0x3f80bf18bea13f75,
0x3f65be16bf393f7b,0xbf7a3f3e3dfbbf62,0xbe893f71bf518000,0xbecfbf043f7fbf22,0xbf27be793f6fbf55,0x3f7cbedbbefc3f7f,0x3f1dbf803f093ec4,0x3cc93f4ebf733e95,
0xbedbbef13f7dbf35,0x3f5cbdc9bf3e3f7b,0xbf803f223e79bf6d,0x3f4ebf753eac3f0e,0x3f71be95bf183f80,0xbf783f463d49bf55,0x3f2cbf7f3f043ec4,0xbe163f62bf673e48,
0x3f67bf623e163f35,0xbf043f7fbf2cbe48,0xbd49bf463f78bec4,0x3f183e95bf713f55,0xbeac3f75bf4e8000,0xbe79bf223f80bf0e,0x3f3e3dc9bf5c3f6d,0xbf7d3ef13edbbf7b,
0xbf513d493f42bf7b,0x3f7ebf04beb83f75,0x3cc9bf4e3f77bec4,0x3ee63edbbf7a3f46,0x3f58bf713ea13f0e,0xbefc3f7dbf39bdc9,0x3f6abe79bf1d3f80,0xbf7f3f2c3e2fbf62,
0x3f13bf803f273e48,0xbdfb3f5cbf6f3e95,0x3f80bf18be893f6d,0xbf653f67be60bf22,0x3f093eacbf733f55,0xbf5f3e163f31bf7f,0xbecf3f78bf4a8000,0xbd97bf3e3f7cbef1,
0x3f62be48bf223f80,0xbf7f3f0e3e95bf6d,0x3f75bf553dc93f35,0xbf463f7bbef1bec4,0x3ef1bf7b3f460000,0xbdc93f55bf753ec4,0xbe95bf0e3f7fbf35,0x3f223e48bf623f6d,
0xbef13f7bbf468000,0x3dc9bf553f75bec4,0x3e953f0ebf7f3f35,0xbf22be483f62bf6d,0x3f62be48bf223f80,0xbf7f3f0e3e95bf6d,0x3f75bf553dc93f35,0xbf463f7bbef1bec4,
0x3f80bf2cbdfb3f55,0xbf733f5cbe2fbf22,0x3f58be16bf273f80,0xbf773edb3ecfbf75,0x3eb8bf713f5fbe48,0xbd973f4ebf7a3ef1,0x3f51bf783ee63ec4,0xbf1d3f80bf31bdc9,
0x3cc93f3ebf7e3f0e,0xbea1bf043f7cbf46,0xbf093f7dbf428000,0x3e89bf673f6abe95,0x3f6fbeacbefc3f7b,0xbf7f3f183e60bf62,0x3f133e79bf653f6d,0xbf4a3d493f39bf7f,
0x3f7dbf463d493f35,0xbf713f62be79bf0e,0x3f5cbf753edb3ec4,0xbf3e3f7fbf18be48,0x3f4ebdc9bf2c3f80,0xbf673e953f04bf7b,0x3f78bef1beac3f6d,0xbf803f223e16bf55,
0x3e163f22bf803f35,0xbeacbef13f78bf55,0x3f043e95bf673f6d,0xbf2cbdc93f4ebf7b,0xbf183f7fbf3e8000,0x3edbbf753f5cbe48,0xbe793f62bf713ec4,0x3d49bf463f7dbf0e,
0x3f7ebf18be2f3f55,0xbf803f2c3d97bf46,0x3f73bedbbeb83f6d,0xbf7a3f043e89bf62,0x3f5fbe79bf093f7b,0xbf6a3eac3ee6bf75,0x3f42bd49bf313f80,0xbf513e163f1dbf7f,
0xbdfb3f4ebf7c3f0e,0x3cc9bf3e3f7fbf22,0xbea13f67bf6f3ec4,0x3e60bf5c3f77bef1,0xbefc3f78bf583e48,0x3ecfbf713f65be95,0xbf273f80bf398000,0x3f13bf7d3f4abdc9,
0xbf8000003f80,0xbf8000003f80,0xbf8000003f80,0xbf8000003f80,0xbf8000003f80,0xbf8000003f80,0xbf8000003f80,0xbf8000003f80,
0x3f808000bf808000,0x3f808000bf808000,0x3f808000bf808000,0x3f808000bf808000,0x3f808000bf808000,0x3f808000bf808000,0x3f808000bf808000,0x3f808000bf808000,
0x3f5fbf04bf583f0e,0x3f6abedbbf653ef1,0x3f42bf2cbf393f35,0x3f51bf18bf4a3f22,0x3f7ebe16bf7c3e48,0x3f80bd49bf7f3dc9,0x3f73beacbf6f3ec4,0x3f7abe79bf773e95,
0x3efc3f5cbf09bf55,0x3ecf3f67bee6bf62,0x3f273f3ebf31bf35,0x3f133f4ebf1dbf46,0x3dfb3f7dbe2fbf7b,0x3cc93f80bd97bf7f,0x3ea13f71beb8bf6d,0x3e603f78be89bf75,
0x3f183f46bf2cbf35,0x3edb3f62bf04bf55,0x3e793f75beacbf6d,0x3d493f7fbe16bf7b,0x3f7d3dc9bf800000,0x3f713e95bf78be48,0x3f5c3ef1bf67bec4,0x3f3e3f22bf4ebf0e,
0xbf4e3f223f3ebf35,0xbf673ef13f5cbf0e,0xbf783e953f71bec4,0xbf803dc93f7dbe48,0xbe163f7f3d49bf80,0xbeac3f753e79bf7b,0xbf043f623edbbf6d,0xbf2c3f463f18bf55,
0xbf6f3edb3f5fbf0e,0xbf7f3e163f7abe95,0xbf133f5c3ee6bf6d,0xbf4a3f2c3f31bf46,0xbcc93f80bdfbbf7b,0xbea13f783e2fbf7f,0x3f093f4ebf27bf35,0x3e893f71becfbf62,
0xbeb8bf673efc3f55,0xbd97bf7d3e603f75,0xbf51bf043f653ec4,0xbf1dbf3e3f393f22,0xbf803d493f7ebe48,0xbf73be793f7c3dc9,0xbf583f183f42bf35,0xbf773eac3f6abef1,
0xbe953f7b3dc9bf80,0xbf223f553ef1bf6d,0xbf623f0e3f46bf35,0xbf7f3e483f75bec4,0xbf75be483f7f0000,0xbf46bf0e3f623ec4,0xbef1bf553f223f35,0xbdc9bf7b3e953f6d,
0xbf75be483f7f8000,0xbf46bf0e3f623ec4,0xbef1bf553f223f35,0xbdc9bf7b3e953f6d,0x3e95bf7bbdc93f80,0x3f22bf55bef13f6d,0x3f62bf0ebf463f35,0x3f7fbe48bf753ec4,
0xbf58bedb3f733e48,0xbefcbf4e3f313f22,0xbf6a3f043f4abf35,0xbf7f3d493f7cbe95,0x3f51bf2cbf273f55,0x3f7ebe79bf6f3ef1,0xbcc9bf7d3e893f6d,0x3ee6bf71be603f7f,
0x3f09bf67bea13f7b,0x3f5fbf18bf393f46,0xbecfbf5c3f1d3f35,0x3d97bf803e2f3f75,0x3f133f3ebf42bf0e,0x3dfb3f78beb8bf62,0x3f80be16bf773ec4,0x3f653eacbf7abdc9,
0x3f71bef1bf4e3f35,0x3f783dc9bf803e48,0x3f2c3f22bf5cbec4,0x3e163f75bedbbf55,0xbf67be953f7d0000,0xbf04bf463f3e3f0e,0x3d49bf7f3e793f6d,0x3f18bf62beac3f7b,
0x3eac3f62bf18bf35,0xbe793f7fbd49bf7b,0xbf3e3f463f04bf6d,0xbf7d3e953f67bf0e,0x3edbbf75be163f80,0x3f5cbf22bf2c3f55,0x3f80bdc9bf783ec4,0x3f4e3ef1bf71be48,
0xbf273f5c3eb8bf7b,0xbf7c3eac3f5fbf22,0x3f1d3f2cbf58bec4,0xbcc93f7dbea1bf62,0x3f65bf18bf313f55,0x3f7a3d49bf7e3e95,0xbe89bf673f133f35,0x3ecfbf78bd973f7f,
0xbf42bf043f6f3e48,0xbe2fbf713efc3f46,0xbf4a3f3e3f09bf6d,0xbf803e163f73bef1,0x3ee63f4ebf39bf0e,0xbe603f80bdfbbf75,0x3f77bedbbf513f35,0x3f6a3e79bf7f3dc9,
0x3f0ebf6dbe483f80,0x3f7bbec4bf553f35,0x3f553ec4bf7b0000,0x3e483f6dbf0ebf35,0xbf0e3f6d3e48bf80,0xbf7b3ec43f55bf35,0xbf55bec43f7b0000,0xbe48bf6d3f0e3f35,
0x3f553ec4bf7b8000,0x3e483f6dbf0ebf35,0xbf0e3f6d3e48bf80,0xbf7b3ec43f55bf35,0xbf55bec43f7b8000,0xbe48bf6d3f0e3f35,0x3f0ebf6dbe483f80,0x3f7bbec4bf553f35,
0xbd973f7dbeb8bf55,0xbf513f3e3efcbf75,0x3f7ebeacbf583f35,0x3f393f04bf73bdc9,0x3ee6bf78bcc93f7b,0x3f7abedbbf4a3f46,0xbf77bd493f7cbec4,0xbecfbf4e3f423ef1,
0xbf7f3e163f6fbf0e,0xbf13bf2c3f5f3e95,0x3dfb3f71bf09bf35,0xbf313f5c3ea1bf7f,0x3f653e79bf803e48,0x3e603f67bf1dbf22,0x3e89bf803e2f3f6d,0x3f6abf18bf273f62,
0xbd49bf753f043f35,0x3f4ebf46bedb3f7b,0x3f713dc9bf7d3ec4,0x3e793f62bf2cbf0e,0x3f3e3ef1bf780000,0xbe163f7fbeacbf55,0xbf673f223f18bf6d,0xbf5cbe953f80be48,
0x3f80be95bf5c3f35,0x3f183f22bf67be48,0xbeac3f7fbe16bf6d,0xbf783ef13f3ebf55,0xbf2c3f623e79bf80,0xbf7d3dc93f71bf0e,0xbedbbf463f4e3ec4,0x3f04bf75bd493f7b,
0xbe603f80bea1bf55,0xbf773f043f31bf62,0x3f6fbf18bf1d3f6d,0x3f423edbbf7c3dc9,0xbf51beac3f7fbe48,0x3dfbbf7d3ecf3f46,0xbcc93f78befcbf35,0xbf653f2c3f09bf75,
0xbf7a3d493f73bf0e,0xbe89bf5c3f393ef1,0x3eb83f4ebf4abec4,0xbf273f673e2fbf7f,0x3f13bf71bd973f7b,0x3f7ebe16bf6a3f22,0xbf803e793f5fbf35,0xbee6bf3e3f583e95,
0xbf463f553e95bf80,0xbf62be483f7fbec4,0x3dc9bf7b3ef13f35,0x3f75bf0ebf223f6d,0x3f223f0ebf750000,0xbef13f7bbdc9bf6d,0xbf7f3e483f62bf35,0xbe95bf553f463ec4,
0xbf22bf0e3f758000,0x3ef1bf7b3dc93f6d,0x3f7fbe48bf623f35,0x3e953f55bf46bec4,0xbf463f553e95bf80,0xbf62be483f7fbec4,0x3dc9bf7b3ef13f35,0x3f75bf0ebf223f6d,
0x3f6abf2cbefc3f7b,0x3f273f04bf7a3dc9,0xbf7c3e163f65bf35,0xbdfbbf673f313ef1,0xbcc9bf713f1d3f0e,0x3f73bf18bf133f75,0xbf093f78bd97bf6d,0xbf773d493f6fbf22,
0x3ecf3f3ebf5fbe48,0xbf423f5c3e60bf7f,0x3e2fbf7d3ee63f35,0x3f7ebedbbf393f62,0x3f80beacbf4a3f55,0x3ea13f4ebf51be95,0xbf58be793f7fbec4,0x3e89bf803eb83f46,
0xbf783dc93f67bf35,0x3d49bf753f183f0e,0x3f7dbef1bf2c3f6d,0x3eac3f46bf5cbe48,0xbf04bf223f710000,0x3f3ebf62be163f7b,0x3f4e3e95bf803ec4,0xbedb3f7fbe79bf55,
0x3e79bf7f3edb3f35,0x3f80be95bf4e3f55,0x3e163f62bf3ebec4,0xbf713f223f04bf7b,0x3f5cbf46beac3f80,0x3f2c3ef1bf7d3e48,0xbf183f75bd49bf6d,0xbf67bdc93f78bf0e,
0x3e893f4ebf58be48,0xbf6f3f2c3ee6bf7f,0xbd97bf673f393ec4,0x3f7cbf04bf1d3f75,0xbdfb3f78bf13bf0e,0xbf803eac3f42bf62,0x3ea1bf803ecf3f35,0x3f7abe16bf5f3f46,
0xbf773f183f09bf7b,0xbeb8bf3e3f653dc9,0x3f7fbedbbf313f6d,0x3e2f3f5cbf4abe95,0xbf7e3e793f51bf55,0x3cc9bf713f273ef1,0x3f73bd49bf6a3f35,0xbe603f7dbefcbf22,
0x3f6dbf35bec43f80,0x3ec43f35bf6d0000,0xbf6d3f353ec4bf80,0xbec4bf353f6d0000,0x3f6dbf35bec43f80,0x3ec43f35bf6d0000,0xbf6d3f353ec4bf80,0xbec4bf353f6d0000,
0x3ec43f35bf6d8000,0xbf6d3f353ec4bf80,0xbec4bf353f6d8000,0x3f6dbf35bec43f80,0x3ec43f35bf6d8000,0xbf6d3f353ec4bf80,0xbec4bf353f6d8000,0x3f6dbf35bec43f80,
0xbf4abe793f7cbf0e,0x3f31bf713d973f62,0x3f653d49bf6f3f35,0xbf093f7dbe89bf46,0xbefcbf183f7abe48,0x3f6abf3ebea13f7f,0x3f273edbbf803ec4,0xbf513f5c3dfbbf75,
0x3f1dbf783e2f3f55,0x3f393eacbf7f3ef1,0xbee63f80beb8bf35,0xbf58be163f77bf22,0x3f5fbf4ebe603f7b,0x3ecf3f2cbf733dc9,0xbf423f673cc9bf6d,0xbf13bf043f7ebe95,
0xbf043f7fbeacbf35,0xbf3ebe953f7dbf0e,0x3f4ebf62bd493f6d,0x3edb3f22bf783e48,0x3e793f46bf670000,0xbf803ef13f18bf7b,0x3e16bf753f2c3ec4,0x3f71bdc9bf5c3f55,
0xbf5cbdc93f71bf35,0x3f2cbf753e163f55,0x3f183ef1bf803ec4,0xbf673f463e79bf7b,0xbf783f223edbbf80,0xbd49bf623f4e3e48,0x3f7dbe95bf3e3f6d,0xbeac3f7fbf04bf0e,
0x3f313eacbf7e3f0e,0xbf653f4e3e2fbf75,0xbf7a3e793f42bf6d,0x3efcbf803ecf3f22,0x3f6fbf3ebe893f7b,0x3d973f5cbf58bdc9,0xbf133f7dbea1bf35,0xbf1dbedb3f80bef1,
0xbf393f71bdfbbf55,0xbee6bf183f7cbe95,0x3e60bf783f273ec4,0x3f5f3d49bf6a3f46,0x3eb83f2cbf773e48,0xbf7f3f043f09bf7f,0xbf51be163f73bf35,0x3f4abf673cc93f62,
0xbf7f3f0e3ef1bf80,0x3e95bf7b3f223ec4,0x3f463e48bf753f35,0xbf623f553dc9bf6d,0xbdc9bf553f620000,0x3f75be48bf463f6d,0xbf223f7bbe95bf35,0xbef1bf0e3f7fbec4,
0xbdc9bf553f628000,0x3f75be48bf463f6d,0xbf223f7bbe95bf35,0xbef1bf0e3f7fbec4,0x3f7fbf0ebef13f80,0xbe953f7bbf22bec4,0xbf46be483f75bf35,0x3f62bf55bdc93f6d,
0xbe2f3f71bf42be48,0xbf4abe163f6fbf46,0xbf39be793f77bf35,0x3f73bf3ebe603f75,0xbf58bd493f65bf55,0x3f5fbf5cbcc93f62,0x3f6abf4ebdfb3f6d,0xbd973f67bf51bdc9,
0xbf7c3eac3f27bf7b,0x3f1dbf7d3eb83f22,0x3f31bf783e893f35,0x3ea13f2cbf7a3e95,0x3f09bf803ee63f0e,0x3efc3f04bf803ef1,0x3ecf3f18bf7e3ec4,0xbf7f3edb3f13bf7f,
0x3f2c3e95bf783f35,0xbf7d3f223eacbf7b,0x3edbbf7f3f183ec4,0x3f043ef1bf803f0e,0x3d49bf623f5c0000,0x3f4e3dc9bf673f55,0xbf713f463e16bf6d,0x3e79bf753f3e3e48,
0xbf3e3f75be79bf35,0xbe16bf463f71be48,0x3f67bdc9bf4e3f6d,0xbf5c3f62bd49bf55,0x3f80bef1bf043f80,0xbf183f7fbedbbf0e,0xbeacbf223f7dbec4,0x3f78be95bf2c3f7b,
0x3f73be79bf313f7b,0xbf583f67bdfbbf46,0xbefc3f80bf13bec4,0xbeb8bf183f7fbef1,0xbf42be163f6abf55,0x3f7cbf2cbe893f75,0x3f4abf713e603f35,0xbcc93f5cbf653dc9,
0xbea13f78bf39be48,0xbf09bedb3f7ebf22,0xbf5f3d493f51bf6d,0x3f6fbf4ebd973f62,0x3f27bf7d3ecf3f0e,0x3e2f3f3ebf773e95,0x3f1d3eacbf7a3f35,0xbf803f043ee6bf7f,
0x3f7bbec4bf0e3f80,0xbf553f6dbe48bf35,0x3e48bf6d3f550000,0x3f0e3ec4bf7b3f35,0xbf7b3ec43f0ebf80,0x3f55bf6d3e483f35,0xbe483f6dbf550000,0xbf0ebec43f7bbf35,
0xbe483f6dbf558000,0xbf0ebec43f7bbf35,0x3f7bbec4bf0e3f80,0xbf553f6dbe48bf35,0x3e48bf6d3f558000,0x3f0e3ec4bf7b3f35,0xbf7b3ec43f0ebf80,0x3f55bf6d3e483f35,
0x3f73bf4ebcc93f55,0xbf093f80bf1dbe95,0x3efc3edbbf7c3f35,0xbf6f3e793f27bf7f,0xbf7f3f043ecfbf7b,0x3f51bf713e893f22,0xbdfbbf3e3f7abec4,0x3f393e16bf653f62,
0x3ea13f18bf803f0e,0xbf583d493f4abf75,0xbf5f3f67be2fbf35,0x3eb8bf783f423dc9,0x3d97bf5c3f6abe48,0x3f133eacbf773f46,0x3f7ebf2cbe603f6d,0xbf313f7dbee6bef1,
0x3f67bf623e163f35,0xbf043f7fbf2cbe48,0xbd49bf463f78bec4,0x3f183e95bf713f55,0xbeac3f75bf4e0000,0xbe79bf223f80bf0e,0x3f3e3dc9bf5c3f6d,0xbf7d3ef13edbbf7b,
0x3edb3ef1bf7d3f35,0xbf5c3dc93f3ebf7b,0x3f80bf22be793f6d,0xbf4e3f75beacbf0e,0xbf713e953f18bf80,0x3f78bf46bd493f55,0xbf2c3f7fbf04bec4,0x3e16bf623f67be48,
0x3f7cbf3ebd973f55,0xbf4a3f78becfbef1,0x3f313e16bf5f3f6d,0xbf733eac3f09bf7f,0xbe603f67bf653e48,0xbe89bf183f80bf22,0xbf6f3f5cbdfbbf35,0x3f27bf803f133e95,
0x3e2f3f2cbf7f3f0e,0xbf1dbe793f6abf62,0xbf393f7dbefcbec4,0x3ea1bf713f58bdc9,0xbf7a3edb3ee6bf7b,0x3f77bf4e3cc93f46,0xbeb8bf043f7ebf35,0x3f423d49bf513f75,
0xbf623e483f22bf80,0x3f7fbf0ebe953f6d,0xbf753f55bdc9bf35,0x3f46bf7b3ef13ec4,0xbef13f7bbf460000,0x3dc9bf553f75bec4,0x3e953f0ebf7f3f35,0xbf22be483f62bf6d,
0x3ef1bf7b3f468000,0xbdc93f55bf753ec4,0xbe95bf0e3f7fbf35,0x3f223e48bf623f6d,0xbf623e483f22bf80,0x3f7fbf0ebe953f6d,0xbf753f55bdc9bf35,0x3f46bf7b3ef13ec4,
0xbf39bd493f4abf7b,0x3f65be79bf133f7f,0xbe60bf183f7fbf35,0x3efc3eacbf6f3f62,0xbf6a3f67be89bf0e,0x3f42bf7d3f093e95,0xbf7c3f043ea1bf6d,0x3f7ebf3ebcc93f46,
0x3f31bf803f1d3e48,0xbee63f78bf513dc9,0x3f7abf4e3d973f35,0xbf5f3f71beb8bef1,0xbecfbedb3f77bf55,0x3f273e16bf583f75,0x3e2fbf5c3f73bec4,0x3dfb3f2cbf803f22,
0xbe16bf223f80bf35,0x3eac3ef1bf783f55,0xbf04be953f67bf6d,0x3f2c3dc9bf4e3f7b,0x3f18bf7f3f3e0000,0xbedb3f75bf5c3e48,0x3e79bf623f71bec4,0xbd493f46bf7d3f0e,
0x3f7dbf463d493f35,0xbf713f62be79bf0e,0x3f5cbf753edb3ec4,0xbf3e3f7fbf18be48,0x3f4ebdc9bf2c3f80,0xbf673e953f04bf7b,0x3f78bef1beac3f6d,0xbf803f223e16bf55,
0x3f4abf7d3f133e48,0xbf393f80bf27bdc9,0x3f65bf713ecf3ec4,0xbf583f78befcbe95,0x3f77bf5c3e603f0e,0xbf6f3f67bea1bef1,0x3f7fbf3e3cc93f35,0xbf7c3f4ebdfbbf22,
0x3f1d3e16bf513f7b,0xbf31bd493f42bf7f,0x3ee63eacbf6a3f6d,0xbf09be793f5fbf75,0x3e893f04bf7a3f55,0xbeb8bedb3f73bf62,0x3d973f2cbf803f35,0xbe2fbf183f7ebf46,
0xbf3500003f353f80,0x3f350000bf35bf80,0xbf3500003f353f80,0x3f350000bf35bf80,0xbf3500003f353f80,0x3f350000bf35bf80,0xbf3500003f353f80,0x3f350000bf35bf80,
0xbf35bf80bf358000,0x3f353f803f358000,0xbf35bf80bf358000,0x3f353f803f358000,0xbf35bf80bf358000,0x3f353f803f358000,0xbf35bf80bf358000,0x3f353f803f358000,
0xbf773f78bf7a3f7b,0xbf6f3f71bf733f75,0xbf7f3f80bf803f80,0xbf7c3f7dbf7e3f7f,0xbf4a3f4ebf513f55,0xbf393f3ebf423f46,0xbf653f67bf6a3f6d,0xbf583f5cbf5f3f62,
0x3e89be793e60be48,0x3eb8beac3ea1be95,0x3d97bd493cc98000,0x3e2fbe163dfbbdc9,0x3f1dbf183f13bf0e,0x3f31bf2c3f27bf22,0x3ee6bedb3ecfbec4,0x3f09bf043efcbef1,
0xbf183f22bf2c3f35,0xbedb3ef1bf043f0e,0xbe793e95beac3ec4,0xbd493dc9be163e48,0xbf7d3f7fbf803f80,0xbf713f75bf783f7b,0xbf5c3f62bf673f6d,0xbf3e3f46bf4e3f55,
0x3f4ebf463f3ebf35,0x3f67bf623f5cbf55,0x3f78bf753f71bf6d,0x3f80bf7f3f7dbf7b,0x3e16bdc93d498000,0x3eacbe953e79be48,0x3f04bef13edbbec4,0x3f2cbf223f18bf0e,
0x3ecfbeac3e89be48,0x3f27bf183f09bef1,0xbe2f3e79bea13ec4,0x3dfbbd49bcc93dc9,0xbf313f3ebf4a3f55,0xbee63f04bf133f22,0xbf7a3f7dbf7f3f80,0xbf5f3f67bf6f3f75,
0x3f6abf713f77bf7b,0x3f42bf4e3f58bf62,0x3f7cbf783f73bf6d,0x3f7ebf803f80bf7f,0x3f39bf2c3f1dbf0e,0x3f65bf5c3f51bf46,0x3e60be163d978000,0x3efcbedb3eb8be95,
0xbf753f7bbf7f3f80,0xbf463f55bf623f6d,0xbef13f0ebf223f35,0xbdc93e48be953ec4,0x3e95be483dc90000,0x3f22bf0e3ef1bec4,0x3f62bf553f46bf35,0x3f7fbf7b3f75bf6d,
0x3e95be483dc98000,0x3f22bf0e3ef1bec4,0x3f62bf553f46bf35,0x3f7fbf7b3f75bf6d,0x3f75bf7b3f7fbf80,0x3f46bf553f62bf6d,0x3ef1bf0e3f22bf35,0x3dc9be483e95bec4,
0xbe603eacbee63f0e,0x3e89be163cc93dc9,0xbf6f3f78bf7e3f80,0xbf273f3ebf513f62,0x3f7cbf803f7fbf7b,0x3f4abf5c3f6abf75,0x3f31bf183efcbec4,0x3f73bf673f58bf46,
0x3f7abf713f65bf55,0x3f77bf7d3f80bf7f,0x3eb8be793dfb8000,0x3f42bf2c3f13bef1,0xbe2f3d493d97be48,0xbf1d3f04becf3e95,0x3f39bf4e3f5fbf6d,0x3ea1bedb3f09bf22,
0x3f71bf623f4ebf35,0x3f78bf7f3f80bf7b,0x3f2cbf463f5cbf6d,0x3e16be953edbbf0e,0xbf673f75bf7d3f80,0xbf043f22bf3e3f55,0x3d493dc9be793ec4,0x3f18bef13eacbe48,
0x3eacbef13f18bf35,0xbe793dc93d49be48,0xbf3e3f22bf043ec4,0xbf7d3f75bf673f55,0x3edbbe953e168000,0x3f5cbf463f2cbf0e,0x3f80bf7f3f78bf6d,0x3f4ebf623f71bf7b,
0x3d97be793ecfbf0e,0xbf133edbbe893dc9,0x3f7ebf803f7abf6d,0x3f31bf4e3f65bf75,0x3ea1be16bcc93e48,0x3f58bf3e3f1dbef1,0xbf5f3f71bf7c3f80,0xbeb83f04bf273f46,
0xbf7f3f78bf6a3f55,0xbf513f67bf773f7f,0xbdfbbd493e60bec4,0xbf393f18bee63e95,0x3f73bf7d3f80bf7b,0x3f09bf2c3f4abf62,0x3efcbeac3e2f8000,0x3f6fbf5c3f42bf22,
0xbf553f6dbf7b3f80,0xbe483ec4bf0e3f35,0x3f0ebec43e480000,0x3f7bbf6d3f55bf35,0x3f55bf6d3f7bbf80,0x3e48bec43f0ebf35,0xbf0e3ec4be480000,0xbf7b3f6dbf553f35,
0x3f0ebec43e488000,0x3f7bbf6d3f55bf35,0x3f55bf6d3f7bbf80,0x3e48bec43f0ebf35,0xbf0e3ec4be488000,0xbf7b3f6dbf553f35,0xbf553f6dbf7b3f80,0xbe483ec4bf0e3f35,
0x3f42bf183ecfbe48,0x3f7cbf803f77bf62,0xbf4a3f67bf7a3f80,0xbcc93e79bee63f22,0xbf733f5cbf393f0e,0xbf583f71bf7e3f7f,0x3efcbf2c3f51bf6d,0xbeb83e163d97be95,
0x3f27bf4e3f6abf7b,0xbe2fbd493e89bef1,0x3f1dbedb3e608000,0x3f80bf783f65bf46,0xbea13f04bf313f55,0x3f09beac3dfb3dc9,0xbf5f3f3ebf133ec4,0xbf6f3f7dbf7f3f75,
0x3d49be953f04bf35,0xbf4e3f22bedb3e48,0xbf713f7fbf7d3f6d,0xbe793ef1bf2c3f55,0xbf3e3f62bf783f80,0x3e163dc9beac3f0e,0x3f67bf463f18bec4,0x3f5cbf753f80bf7b,
0xbf803f75bf5c3f35,0xbf183f46bf673f7b,0x3eacbdc9be163ec4,0x3f78bf623f3ebf0e,0x3f2cbef13e798000,0x3f7dbf7f3f71bf55,0x3edbbf223f4ebf6d,0xbf043e95bd49be48,
0xbf093f3ebf653f7b,0x3efcbe79bcc93e95,0xbecf3e163dfbbec4,0xbf7f3f71bf513f22,0x3f7cbf673f42bf0e,0x3f1dbf4e3f6fbf7f,0xbf313f5cbf773f80,0x3ea1bd49be603ef1,
0x3f58bf2c3ee6be48,0x3f5fbf783f80bf75,0xbf6a3f7dbf7e3f6d,0xbd973eacbf133f46,0x3e2fbedb3f27bf55,0xbf4a3f18beb83dc9,0x3f39bf043e898000,0x3f73bf803f7abf62,
0xbf223f55bf753f80,0x3ef1be48bdc93ec4,0x3f7fbf7b3f62bf35,0x3e95bf0e3f46bf6d,0xbf463f0ebe950000,0xbf623f7bbf7f3f6d,0x3dc93e48bef13f35,0x3f75bf553f22bec4,
0x3f46bf0e3e958000,0x3f62bf7b3f7fbf6d,0xbdc9be483ef1bf35,0xbf753f55bf223ec4,0xbf223f55bf753f80,0x3ef1be48bdc93ec4,0x3f7fbf7b3f62bf35,0x3e95bf0e3f46bf6d,
0x3f6fbf803f77bf55,0xbd97be793f09bf46,0xbf133f4ebf733f80,0x3f1dbeac3cc93e95,0x3f31bedb3dfb3e48,0x3f65bf7d3f7cbf62,0xbf7a3f5cbf273ec4,0xbefc3f3ebf6a3f7f,
0xbeb83d493e89bf0e,0xbf7f3f78bf583f22,0x3f51bf183ea18000,0x3f4abf713f80bf75,0x3f39bf673f7ebf7b,0xbee63e163e2fbef1,0xbe603f04bf423f6d,0x3f5fbf2c3ecfbdc9,
0xbf783f7fbf673f35,0x3d493e95bf183f55,0x3f7dbf623f2cbec4,0x3eacbf223f5cbf7b,0xbf043f46bf713f80,0x3f3ebef13e163e48,0x3f4ebf753f80bf6d,0xbedb3dc93e79bf0e,
0x3e793dc9bedb3f35,0x3f80bf753f4ebf0e,0x3e16bef13f3ebf6d,0xbf713f46bf043e48,0x3f5cbf223eac8000,0x3f2cbf623f7dbf7b,0xbf183e953d49bec4,0xbf673f7fbf783f55,
0x3f5fbf7d3f7abf55,0xbecf3d493ea1bf22,0xbf423f71bf803f6d,0x3f13be79bdfb3ef1,0x3f1dbf5c3f7cbf7b,0xbf393edbbd97be95,0xbee63f3ebf6f3f80,0x3f58bf183e893dc9,
0xbefc3e163e60bf0e,0xbf6a3f80bf733f46,0x3f27beacbcc93ec4,0x3f51bf783f7ebf62,0xbf4a3f04be2fbe48,0xbf313f67bf7f3f75,0x3f65bf2c3eb88000,0x3f09bf4e3f77bf7f,
0xbec43f35bf6d3f80,0x3f6dbf353ec40000,0x3ec4bf353f6dbf80,0xbf6d3f35bec40000,0xbec43f35bf6d3f80,0x3f6dbf353ec40000,0x3ec4bf353f6dbf80,0xbf6d3f35bec40000,
0x3f6dbf353ec48000,0x3ec4bf353f6dbf80,0xbf6d3f35bec48000,0xbec43f35bf6d3f80,0x3f6dbf353ec48000,0x3ec4bf353f6dbf80,0xbf6d3f35bec48000,0xbec43f35bf6d3f80,
0x3dfbbf043f51bf7b,0xbf803f67bf273e95,0xbea13f2cbf6a3f80,0x3f7abf4e3efcbdc9,0xbe89be163f09bf55,0xbf6f3f80bf653f22,0x3d973eacbf313f6d,0x3f7cbf783f4abef1,
0xbf7e3f5cbf133e48,0xbcc93edbbf423f75,0x3f73bf3e3ecf8000,0x3e60bf183f5fbf7f,0xbf773f7dbf583f0e,0x3eb83d49bee63f46,0x3f7fbf713f39bec4,0xbe2fbe793f1dbf62,
0x3f04bdc9beac3f35,0x3f3ebf753f7dbf55,0xbf4e3ef1bd49bec4,0xbedb3f46bf783f7b,0xbe793f22bf673f80,0x3f80bf623f18be48,0xbe16be953f2cbf6d,0xbf713f7fbf5c3f0e,
0x3f5cbf7f3f71bf35,0xbf2c3e953e16bf0e,0xbf183f62bf803f6d,0x3f67bf223e793e48,0x3f78bf463edb8000,0x3d49bef13f4ebf7b,0xbf7d3f75bf3e3ec4,0x3eac3dc9bf043f55,
0xbf803f67bf1d3e48,0x3ea13e16bf133f62,0x3f58bf043d973ec4,0x3e89bf2c3f6fbf7f,0xbecfbd493efcbf55,0xbf423f78bf7a3f46,0xbe2f3f18bf653f80,0x3f7ebf713f31be95,
0x3cc93edbbf4a3f7b,0x3f73bf7d3f51bef1,0x3f09bf5c3f7fbf6d,0xbf773f3ebeb8bdc9,0xbf6a3f80bf5f3f0e,0x3f27be79be603f22,0x3f7cbf4e3ee68000,0xbdfbbeac3f39bf75,
0xbdc93f0ebf623f80,0x3f75bf7b3f46bec4,0xbf223e483e95bf35,0xbef13f55bf7f3f6d,0x3f7fbf553ef10000,0xbe95be483f22bf6d,0xbf463f7bbf753f35,0x3f62bf0e3dc93ec4,
0x3f7fbf553ef18000,0xbe95be483f22bf6d,0xbf463f7bbf753f35,0x3f62bf0e3dc93ec4,0x3dc9bf0e3f62bf80,0xbf753f7bbf463ec4,0x3f22be48be953f35,0x3ef1bf553f7fbf6d,
0xbf513edb3d97bf0e,0xbdfb3f18bf6a3f7f,0xbcc93f04bf5f3f80,0x3f65bf803f58bef1,0xbe603f2cbf733f7b,0x3f77bf783f39be95,0x3f6fbf7d3f4abec4,0xbf423eac3e2fbf22,
0xbf133f67bf7f3f55,0x3f7ebf4e3ecf3dc9,0x3f80bf5c3efc8000,0xbee6bd493f09bf62,0x3f7abf3e3ea13e48,0xbe89be793f31bf75,0xbeb8be163f1dbf6d,0xbf273f71bf7c3f46,
0x3f2cbf753f78bf35,0xbf7d3f46beacbe48,0x3edb3dc9bf183f6d,0x3f04bf623f80bf55,0x3d493ef1bf5c3f80,0x3f4ebf7f3f67bf0e,0xbf713f22be16bec4,0x3e793e95bf3e3f7b,
0xbf3e3e953e79bf35,0xbe163f22bf713f7b,0x3f67bf7f3f4ebec4,0xbf5c3ef13d49bf0e,0x3f80bf623f048000,0xbf183dc93edbbf55,0xbeac3f46bf7d3f6d,0x3f78bf753f2cbe48,
0x3f65bf04bcc93f0e,0xbe60beac3f4abf7f,0x3e89bf3e3f7cbf6d,0xbf6a3f7dbf423e95,0xbf7f3f4ebeb8be48,0x3f13bd49befc3f62,0x3dfb3edbbf583f80,0x3f31bf783f73bf22,
0x3ee6bf5c3f80bf55,0xbf7a3f71bf1d3dc9,0xbf773f2cbe2fbec4,0x3ecf3e16bf273f75,0xbd973f18bf6f3f7b,0x3f51bf803f5fbef1,0x3f7ebf673f098000,0xbf393e793ea1bf46,
0x3e483ec4bf553f80,0x3f0ebf6d3f7bbf35,0xbf7b3f6dbf0e0000,0x3f55bec4be483f35,0xbe48bec43f55bf80,0xbf0e3f6dbf7b3f35,0x3f7bbf6d3f0e0000,0xbf553ec43e48bf35,
0x3f7bbf6d3f0e8000,0xbf553ec43e48bf35,0x3e483ec4bf553f80,0x3f0ebf6d3f7bbf35,0xbf7b3f6dbf0e8000,0x3f55bec4be483f35,0xbe48bec43f55bf80,0xbf0e3f6dbf7b3f35,
0xbf653f7dbf393e48,0x3f7abf2c3dfb3ef1,0x3e893eacbf513f80,0x3ecfbf5c3f7fbf46,0x3f27bf783f6fbf0e,0xbf7c3f67befcbdc9,0xbf1d3d493f09bf6d,0xbcc93f18bf733f75,
0x3ee63e16bf313f7b,0x3e60bf3e3f7ebf62,0x3f77bf713f138000,0xbf6a3f043d97bf22,0xbf423e793eb8bf55,0x3e2f3edbbf5f3f7f,0xbf4a3f80bf583ec4,0x3f80bf4e3ea13e95,
0xbf673ef13e16bf35,0x3f043dc9bf2c3f7b,0x3d49bf223f78bf6d,0xbf183f75bf713f0e,0x3eac3e95bf4e3f80,0x3e79bf463f80bf55,0xbf3e3f7fbf5c3ec4,0x3f7dbf623edb3e48,
0xbedb3f62bf7d3f35,0x3f5cbf7f3f3ebe48,0xbf803f46be79bec4,0x3f4ebe95beac3f55,0x3f71bf753f188000,0xbf783f22bd49bf0e,0x3f2cbdc9bf043f6d,0xbe16bef13f67bf7b,
0xbf13bd493f27bf7b,0x3dfb3f04bf6f3f75,0xbf803f4ebe89bec4,0x3f65bedbbe603f46,0xbf093f71bf733f0e,0x3f5fbf7d3f31bdc9,0x3ecf3e79bf4a3f80,0x3d97bf2c3f7cbf62,
0xbf513f80bf423e48,0x3f7ebf5c3eb83e95,0x3cc93f18bf773f6d,0x3ee6bf673f7abf22,0x3f58beacbea13f55,0xbefcbe163f39bf7f,0x3f6abf783f1d8000,0xbf7f3f3ebe2fbef1,
0x3ef13e48bf463f80,0xbdc9bf0e3f75bf6d,0xbe953f55bf7f3f35,0x3f22bf7b3f62bec4,0xbf623f7bbf220000,0x3f7fbf553e953ec4,0xbf753f0e3dc9bf35,0x3f46be48bef13f6d,
0x3f62bf7b3f228000,0xbf7f3f55be95bec4,0x3f75bf0ebdc93f35,0xbf463e483ef1bf6d,0x3ef13e48bf463f80,0xbdc9bf0e3f75bf6d,0xbe953f55bf7f3f35,0x3f22bf7b3f62bec4,
0xbcc93f2cbf7e3f55,0x3ea1bf5c3f7cbf22,0x3f093e16bf423f80,0xbe89bedb3f6abf75,0xbf6f3f71befcbe48,0x3f7fbf4e3e603ef1,0xbf133f78bf653ec4,0x3f4abf803f39bdc9,
0x3f80bf3e3dfb3f0e,0xbf733f043e2fbf46,0x3f58bf7d3f278000,0xbf773f67becfbe95,0x3eb83eacbf5f3f7b,0xbd97bf183f7abf62,0x3f51be79bee63f6d,0xbf1dbd493f31bf7f,
0xbe163f46bf803f35,0x3eacbf623f78bf0e,0xbf043f75bf673ec4,0x3f2cbf7f3f4ebe48,0x3f183dc9bf3e3f80,0xbedbbe953f5cbf7b,0x3e793ef1bf713f6d,0xbd49bf223f7dbf55,
0x3f7dbf22bd493f35,0xbf713ef13e79bf55,0x3f5cbe95bedb3f6d,0xbf3e3dc93f18bf7b,0x3f4ebf7f3f2c8000,0xbf673f75bf04be48,0x3f78bf623eac3ec4,0xbf803f46be16bf0e,
0x3dfb3f18bf7c3f55,0xbcc9bf2c3f7fbf46,0x3ea13edbbf6f3f6d,0xbe60bf043f77bf62,0x3efc3e79bf583f7b,0xbecfbeac3f65bf75,0x3f273d49bf393f80,0xbf13be163f4abf7f,
0x3f7ebf4e3e2f3f0e,0xbf803f3ebd97bf22,0x3f73bf673eb83ec4,0xbf7a3f5cbe89bef1,0x3f5fbf783f093e48,0xbf6a3f71bee6be95,0x3f42bf803f318000,0xbf513f7dbf1dbdc9,
0xbf3500003f353f80,0x3f350000bf35bf80,0xbf3500003f353f80,0x3f350000bf35bf80,0xbf3500003f353f80,0x3f350000bf35bf80,0xbf3500003f353f80,0x3f350000bf35bf80,
0xbf35bf80bf358000,0x3f353f803f358000,0xbf35bf80bf358000,0x3f353f803f358000,0xbf35bf80bf358000,0x3f353f803f358000,0xbf35bf80bf358000,0x3f353f803f358000,
0xbefc3f04bf093f0e,0xbecf3edbbee63ef1,0xbf273f2cbf313f35,0xbf133f18bf1d3f22,0xbdfb3e16be2f3e48,0xbcc93d49bd973dc9,0xbea13eacbeb83ec4,0xbe603e79be893e95,
0x3f5fbf5c3f58bf55,0x3f6abf673f65bf62,0x3f42bf3e3f39bf35,0x3f51bf4e3f4abf46,0x3f7ebf7d3f7cbf7b,0x3f80bf803f7fbf7f,0x3f73bf713f6fbf6d,0x3f7abf783f77bf75,
0x3f4ebf463f3ebf35,0x3f67bf623f5cbf55,0x3f78bf753f71bf6d,0x3f80bf7f3f7dbf7b,0x3e16bdc93d490000,0x3eacbe953e79be48,0x3f04bef13edbbec4,0x3f2cbf223f18bf0e,
0x3f18bf223f2cbf35,0x3edbbef13f04bf0e,0x3e79be953eacbec4,0x3d49bdc93e16be48,0x3f7dbf7f3f80bf80,0x3f71bf753f78bf7b,0x3f5cbf623f67bf6d,0x3f3ebf463f4ebf55,
0x3eb8bedb3efcbf0e,0x3d97be163e60be95,0x3f51bf5c3f65bf6d,0x3f1dbf2c3f39bf46,0x3f80bf803f7ebf7b,0x3f73bf783f7cbf7f,0x3f58bf4e3f42bf35,0x3f77bf713f6abf62,
0xbf6f3f67bf5f3f55,0xbf7f3f7dbf7a3f75,0xbf133f04bee63ec4,0xbf4a3f3ebf313f22,0xbcc9bd493dfbbe48,0xbea13e79be2f3dc9,0x3f09bf183f27bf35,0x3e89beac3ecfbef1,
0x3f75bf7b3f7fbf80,0x3f46bf553f62bf6d,0x3ef1bf0e3f22bf35,0x3dc9be483e95bec4,0xbe953e48bdc90000,0xbf223f0ebef13ec4,0xbf623f55bf463f35,0xbf7f3f7bbf753f6d,
0xbe953e48bdc98000,0xbf223f0ebef13ec4,0xbf623f55bf463f35,0xbf7f3f7bbf753f6d,0xbf753f7bbf7f3f80,0xbf463f55bf623f6d,0xbef13f0ebf223f35,0xbdc93e48be953ec4,
0xbf093edbbea13e48,0xbf5f3f4ebf393f22,0x3ecfbf043f1dbf35,0xbd97bd493e2fbe95,0xbf133f2cbf423f55,0xbdfb3e79beb83ef1,0xbf803f7dbf773f6d,0xbf653f71bf7a3f7f,
0xbf583f67bf733f7b,0xbefc3f18bf313f46,0xbf6a3f5cbf4a3f35,0xbf7f3f80bf7c3f75,0x3f51bf3e3f27bf0e,0x3f7ebf783f6fbf62,0xbcc93e16be893ec4,0x3ee6beac3e60bdc9,
0xbeac3ef1bf183f35,0x3e79bdc9bd493e48,0x3f3ebf223f04bec4,0x3f7dbf753f67bf55,0xbedb3e95be160000,0xbf5c3f46bf2c3f0e,0xbf803f7fbf783f6d,0xbf4e3f62bf713f7b,
0x3f71bf623f4ebf35,0x3f78bf7f3f80bf7b,0x3f2cbf463f5cbf6d,0x3e16be953edbbf0e,0xbf673f75bf7d3f80,0xbf043f22bf3e3f55,0x3d493dc9be793ec4,0x3f18bef13eacbe48,
0x3f42bf5c3f6fbf7b,0x3e2fbeac3efcbf22,0x3f4abf2c3f09bec4,0x3f80bf7d3f73bf62,0xbee63f18bf393f55,0x3e60bd49bdfb3e95,0xbf773f67bf513f35,0xbf6a3f78bf7f3f7f,
0xbf273f04beb83e48,0xbf7c3f71bf5f3f46,0x3f1dbf3e3f58bf6d,0xbcc9be163ea1bef1,0x3f65bf4e3f31bf0e,0x3f7abf803f7ebf75,0xbe893edbbf133f35,0x3ecfbe793d973dc9,
0xbf553f6dbf7b3f80,0xbe483ec4bf0e3f35,0x3f0ebec43e480000,0x3f7bbf6d3f55bf35,0x3f55bf6d3f7bbf80,0x3e48bec43f0ebf35,0xbf0e3ec4be480000,0xbf7b3f6dbf553f35,
0x3f0ebec43e488000,0x3f7bbf6d3f55bf35,0x3f55bf6d3f7bbf80,0x3e48bec43f0ebf35,0xbf0e3ec4be488000,0xbf7b3f6dbf553f35,0xbf553f6dbf7b3f80,0xbe483ec4bf0e3f35,
0x3f7fbf7d3f6fbf55,0x3f13bf3e3f5fbf75,0xbdfb3eacbf093f35,0x3f31bf043ea1bdc9,0xbf653f78bf803f7b,0xbe603edbbf1d3f46,0xbe893d493e2fbec4,0xbf6a3f4ebf273ef1,
0xbd97be163eb8bf0e,0xbf513f2cbefc3e95,0x3f7ebf713f58bf35,0x3f39bf5c3f73bf7f,0x3ee6be793cc93e48,0x3f7abf673f4abf22,0xbf773f80bf7c3f6d,0xbecf3f18bf423f62,
0xbf803f75bf5c3f35,0xbf183f46bf673f7b,0x3eacbdc9be163ec4,0x3f78bf623f3ebf0e,0x3f2cbef13e790000,0x3f7dbf7f3f71bf55,0x3edbbf223f4ebf6d,0xbf043e95bd49be48,
0xbd493e95bf043f35,0x3f4ebf223edbbe48,0x3f71bf7f3f7dbf6d,0x3e79bef13f2cbf55,0x3f3ebf623f78bf80,0xbe16bdc93eacbf0e,0xbf673f46bf183ec4,0xbf5c3f75bf803f7b,
0x3f7abf803f73bf55,0x3e89bf043f39bf62,0xbeb83f18bf4a3f6d,0x3f27bedb3e2f3dc9,0xbf133eacbd97be48,0xbf7e3f7dbf6a3f46,0x3f80bf783f5fbf35,0x3ee6bf2c3f58bf75,
0xbe60bd493ea1bf0e,0xbf773f5cbf313ef1,0x3f6fbf4e3f1dbec4,0x3f42bf673f7cbf7f,0xbf513f71bf7f3f7b,0x3dfb3e16becf3f22,0xbcc9be793efcbf35,0xbf653f3ebf093e95,
0x3f22bf553f75bf80,0xbef13e483dc9bec4,0xbf7f3f7bbf623f35,0xbe953f0ebf463f6d,0x3f46bf0e3e950000,0x3f62bf7b3f7fbf6d,0xbdc9be483ef1bf35,0xbf753f55bf223ec4,
0xbf463f0ebe958000,0xbf623f7bbf7f3f6d,0x3dc93e48bef13f35,0x3f75bf553f22bec4,0x3f22bf553f75bf80,0xbef13e483dc9bec4,0xbf7f3f7bbf623f35,0xbe953f0ebf463f6d,
0xbecf3f2cbf5f3f7b,0x3f42bf043e603dc9,0xbe2fbe163ee6bf35,0xbf7e3f67bf393ef1,0xbf803f71bf4a3f0e,0xbea13f18bf513f75,0x3f58bf783f7fbf6d,0xbe89bd493eb8bf22,
0x3f6abf3e3efcbe48,0x3f27bf5c3f7abf7f,0xbf7c3f7dbf653f35,0xbdfb3edbbf313f62,0xbcc93eacbf1d3f55,0x3f73bf4e3f13be95,0xbf093e793d97bec4,0xbf773f80bf6f3f46,
0xbe79bdc93edbbf35,0xbf803f75bf4e3f0e,0xbe163ef1bf3e3f6d,0x3f71bf463f04be48,0xbf5c3f22beac0000,0xbf2c3f62bf7d3f7b,0x3f18be95bd493ec4,0x3f67bf7f3f78bf55,
0xbf783f7fbf673f35,0x3d493e95bf183f55,0x3f7dbf623f2cbec4,0x3eacbf223f5cbf7b,0xbf043f46bf713f80,0x3f3ebef13e163e48,0x3f4ebf753f80bf6d,0xbedb3dc93e79bf0e,
0x3f77bf4e3f09be48,0x3eb8bf2c3f65bf7f,0xbf7f3f67bf313ec4,0xbe2f3f04bf4a3f75,0x3f7ebf783f51bf0e,0xbcc9beac3f27bf62,0xbf733f80bf6a3f35,0x3e603e16befc3f46,
0x3e89bf183f58bf7b,0xbf6f3f3ebee63dc9,0xbd973edbbf393f6d,0x3f7cbf5c3f1dbe95,0xbdfbbe793f13bf55,0xbf803f71bf423ef1,0x3ea13d49becf3f35,0x3f7abf7d3f5fbf22,
0xbec43f35bf6d3f80,0x3f6dbf353ec40000,0x3ec4bf353f6dbf80,0xbf6d3f35bec40000,0xbec43f35bf6d3f80,0x3f6dbf353ec40000,0x3ec4bf353f6dbf80,0xbf6d3f35bec40000,
0x3f6dbf353ec48000,0x3ec4bf353f6dbf80,0xbf6d3f35bec48000,0xbec43f35bf6d3f80,0x3f6dbf353ec48000,0x3ec4bf353f6dbf80,0xbf6d3f35bec48000,0xbec43f35bf6d3f80,
0xbf1d3e793e2fbf0e,0xbf393f71bf7f3f62,0x3ee6bd49beb83f35,0x3f58bf7d3f77bf46,0xbf5f3f18be60be48,0xbecf3f3ebf733f7f,0x3f42bedb3cc93ec4,0x3f13bf5c3f7ebf75,
0xbf4a3f78bf7c3f55,0x3f31beacbd973ef1,0x3f65bf803f6fbf35,0xbf093e163e89bf22,0xbefc3f4ebf7a3f7b,0x3f6abf2c3ea13dc9,0x3f27bf673f80bf6d,0xbf513f04bdfbbe95,
0x3f5cbf7f3f71bf35,0xbf2c3e953e16bf0e,0xbf183f62bf803f6d,0x3f67bf223e793e48,0x3f78bf463edb0000,0x3d49bef13f4ebf7b,0xbf7d3f75bf3e3ec4,0x3eac3dc9bf043f55,
0xbf043dc93eacbf35,0xbf3e3f75bf7d3f55,0x3f4ebef13d493ec4,0x3edbbf463f78bf7b,0x3e79bf223f67bf80,0xbf803f62bf183e48,0x3e163e95bf2c3f6d,0x3f71bf7f3f5cbf0e,
0x3f39beacbdfb3f0e,0x3ee6bf4e3f7cbf75,0xbe60be793f27bf6d,0xbf5f3f80bf6a3f22,0xbeb83f3ebf773f7b,0x3f7fbf5c3f09bdc9,0x3f51bf7d3f73bf35,0xbf4a3edb3cc9bef1,
0x3f31bf713f7ebf55,0xbf653f18be2fbe95,0xbf7a3f78bf423ec4,0x3efcbd49becf3f46,0x3f6fbf2c3e893e48,0x3d97bf043f58bf7f,0xbf133e163ea1bf35,0xbf1d3f67bf803f62,
0x3dc9bf0e3f62bf80,0xbf753f7bbf463ec4,0x3f22be48be953f35,0x3ef1bf553f7fbf6d,0xbf7f3f55bef10000,0x3e953e48bf223f6d,0x3f46bf7b3f75bf35,0xbf623f0ebdc9bec4,
0xbf7f3f55bef18000,0x3e953e48bf223f6d,0x3f46bf7b3f75bf35,0xbf623f0ebdc9bec4,0xbdc93f0ebf623f80,0x3f75bf7b3f46bec4,0xbf223e483e95bf35,0xbef13f55bf7f3f6d,
0x3f7cbf713f27be48,0xbf1d3e163eb8bf46,0xbf313e793e89bf35,0xbea13f3ebf7a3f75,0xbf093d493ee6bf55,0xbefc3f5cbf803f62,0xbecf3f4ebf7e3f6d,0x3f7fbf673f13bdc9,
0xbe2fbeac3f42bf7b,0xbf4a3f7dbf6f3f22,0xbf393f78bf773f35,0x3f73bf2c3e603e95,0xbf583f80bf653f0e,0x3f5fbf043cc93ef1,0x3f6abf183dfb3ec4,0xbd97bedb3f51bf7f,
0x3f3ebe95be793f35,0x3e16bf223f71bf7b,0xbf673f7fbf4e3ec4,0x3f5cbef1bd493f0e,0xbf803f62bf040000,0x3f18bdc9bedb3f55,0x3eacbf463f7dbf6d,0xbf783f75bf2c3e48,
0x3f2cbf753f78bf35,0xbf7d3f46beacbe48,0x3edb3dc9bf183f6d,0x3f04bf623f80bf55,0x3d493ef1bf5c3f80,0x3f4ebf7f3f67bf0e,0xbf713f22be16bec4,0x3e793e95bf3e3f7b,
0x3ea13e79bf393f7b,0x3f09bf673f7ebf46,0x3f5fbf803f51bec4,0xbf6f3f18bd97bef1,0xbf273e163ecfbf55,0xbe2f3f2cbf773f75,0xbf1d3f71bf7a3f35,0x3f80bf5c3ee63dc9,
0x3f73bf783f31be48,0xbf583edb3dfbbf22,0xbefcbd493f13bf6d,0xbeb83f4ebf7f3f62,0xbf423f7dbf6a3f0e,0x3f7cbf3e3e893e95,0x3f4abeacbe603f35,0xbcc9bf043f65bf7f,
0x3e483ec4bf553f80,0x3f0ebf6d3f7bbf35,0xbf7b3f6dbf0e0000,0x3f55bec4be483f35,0xbe48bec43f55bf80,0xbf0e3f6dbf7b3f35,0x3f7bbf6d3f0e0000,0xbf553ec43e48bf35,
0x3f7bbf6d3f0e8000,0xbf553ec43e48bf35,0x3e483ec4bf553f80,0x3f0ebf6d3f7bbf35,0xbf7b3f6dbf0e8000,0x3f55bec4be483f35,0xbe48bec43f55bf80,0xbf0e3f6dbf7b3f35,
0xbea13f4ebf803f55,0x3f58bf803f4abe95,0x3f5fbedbbe2f3f35,0xbeb8be793f42bf7f,0xbd97bf043f6abf7b,0xbf133f71bf773f22,0xbf7e3f3ebe60bec4,0x3f31be16bee63f62,
0x3f73bf183cc93f0e,0xbf09bd493f1dbf75,0x3efcbf673f7cbf35,0xbf6f3f78bf273dc9,0xbf7f3f5cbecfbe48,0x3f51beacbe893f46,0xbdfb3f2cbf7a3f6d,0x3f39bf7d3f65bef1,
0xbedb3f62bf7d3f35,0x3f5cbf7f3f3ebe48,0xbf803f46be79bec4,0x3f4ebe95beac3f55,0x3f71bf753f180000,0xbf783f22bd49bf0e,0x3f2cbdc9bf043f6d,0xbe16bef13f67bf7b,
0x3f67bef1be163f35,0xbf04bdc93f2cbf7b,0xbd493f22bf783f6d,0x3f18bf753f71bf0e,0xbeacbe953f4ebf80,0xbe793f46bf803f55,0x3f3ebf7f3f5cbec4,0xbf7d3f62bedbbe48,
0xbe2f3f3ebf7f3f55,0x3f1dbf783f6abef1,0x3f39be16befc3f6d,0xbea1beac3f58bf7f,0x3f7abf673ee63e48,0xbf773f183cc9bf22,0x3eb8bf5c3f7ebf35,0xbf423f80bf513e95,
0x3f7cbf2c3d973f0e,0xbf4a3e793ecfbf62,0x3f31bf7d3f5fbec4,0xbf733f71bf09bdc9,0xbe60bedb3f65bf7b,0xbe893f4ebf803f46,0xbf6f3f043dfbbf35,0x3f27bd49bf133f75,
0xbef1be483f46bf80,0x3dc93f0ebf753f6d,0x3e95bf553f7fbf35,0xbf223f7bbf623ec4,0x3f62bf7b3f220000,0xbf7f3f55be95bec4,0x3f75bf0ebdc93f35,0xbf463e483ef1bf6d,
0xbf623f7bbf228000,0x3f7fbf553e953ec4,0xbf753f0e3dc9bf35,0x3f46be48bef13f6d,0xbef1be483f46bf80,0x3dc93f0ebf753f6d,0x3e95bf553f7fbf35,0xbf223f7bbf623ec4,
0xbf313d493f1dbf7b,0x3ee63e79bf513f7f,0xbf7a3f183d97bf35,0x3f5fbeacbeb83f62,0x3ecfbf673f77bf0e,0xbf273f7dbf583e95,0xbe2fbf043f73bf6d,0xbdfb3f3ebf803f46,
0xbf393f80bf4a3e48,0x3f65bf783f133dc9,0xbe603f4ebf7f3f35,0x3efcbf713f6fbef1,0xbf6a3edb3e89bf55,0x3f42be16bf093f75,0xbf7c3f5cbea1bec4,0x3f7ebf2c3cc93f22,
0xbf7d3f223d49bf35,0x3f71bef1be793f55,0xbf5c3e953edbbf6d,0x3f3ebdc9bf183f7b,0xbf4e3f7fbf2c0000,0x3f67bf753f043e48,0xbf783f62beacbec4,0x3f80bf463e163f0e,
0xbe163f46bf803f35,0x3eacbf623f78bf0e,0xbf043f75bf673ec4,0x3f2cbf7f3f4ebe48,0x3f183dc9bf3e3f80,0xbedbbe953f5cbf7b,0x3e793ef1bf713f6d,0xbd49bf223f7dbf55,
0xbf1d3f7dbf513e48,0x3f31bf803f42bdc9,0xbee63f71bf6a3ec4,0x3f09bf783f5fbe95,0xbe893f5cbf7a3f0e,0x3eb8bf673f73bef1,0xbd973f3ebf803f35,0x3e2fbf4e3f7ebf22,
0x3f4abe16bf133f7b,0xbf393d493f27bf7f,0x3f65beacbecf3f6d,0xbf583e793efcbf75,0x3f77bf04be603f55,0xbf6f3edb3ea1bf62,0x3f7fbf2cbcc93f35,0xbf7c3f183dfbbf46,
0x3f350000bf353f80,0xbf3500003f35bf80,0x3f350000bf353f80,0xbf3500003f35bf80,0x3f350000bf353f80,0xbf3500003f35bf80,0x3f350000bf353f80,0xbf3500003f35bf80,
0xbf353f80bf358000,0x3f35bf803f358000,0xbf353f80bf358000,0x3f35bf803f358000,0xbf353f80bf358000,0x3f35bf803f358000,0xbf353f80bf358000,0x3f35bf803f358000,
0xbe89bf783e603f7b,0xbeb8bf713ea13f75,0xbd97bf803cc93f80,0xbe2fbf7d3dfb3f7f,0xbf1dbf4e3f133f55,0xbf31bf3e3f273f46,0xbee6bf673ecf3f6d,0xbf09bf5c3efc3f62,
0xbf773e793f7abe48,0xbf6f3eac3f73be95,0xbf7f3d493f808000,0xbf7c3e163f7ebdc9,0xbf4a3f183f51bf0e,0xbf393f2c3f42bf22,0xbf653edb3f6abec4,0xbf583f043f5fbef1,
0xbf4ebf223f3e3f35,0xbf67bef13f5c3f0e,0xbf78be953f713ec4,0xbf80bdc93f7d3e48,0xbe16bf7f3d493f80,0xbeacbf753e793f7b,0xbf04bf623edb3f6d,0xbf2cbf463f183f55,
0xbf183f463f2cbf35,0xbedb3f623f04bf55,0xbe793f753eacbf6d,0xbd493f7f3e16bf7b,0xbf7d3dc93f808000,0xbf713e953f78be48,0xbf5c3ef13f67bec4,0xbf3e3f223f4ebf0e,
0xbf6a3eac3f77be48,0xbf423f183f58bef1,0xbf7cbe793f733ec4,0xbf7e3d493f803dc9,0xbf39bf3e3f1d3f55,0xbf65bf043f513f22,0xbe60bf7d3d973f80,0xbefcbf673eb83f75,
0x3ecf3f71be89bf7b,0x3f273f4ebf09bf62,0xbe2f3f783ea1bf6d,0x3dfb3f803cc9bf7f,0xbf313f2c3f4abf0e,0xbee63f5c3f13bf46,0xbf7a3e163f7f8000,0xbf5f3edb3f6fbe95,
0xbe95bf7b3dc93f80,0xbf22bf553ef13f6d,0xbf62bf0e3f463f35,0xbf7fbe483f753ec4,0xbf753e483f7f0000,0xbf463f0e3f62bec4,0xbef13f553f22bf35,0xbdc93f7b3e95bf6d,
0xbf753e483f7f8000,0xbf463f0e3f62bec4,0xbef13f553f22bf35,0xbdc93f7b3e95bf6d,0x3e953f7bbdc9bf80,0x3f223f55bef1bf6d,0x3f623f0ebf46bf35,0x3f7f3e48bf75bec4,
0xbf7abeac3f653f0e,0xbf773e163f803dc9,0xbeb8bf783dfb3f80,0xbf42bf3e3f133f62,0x3e2f3f803d97bf7b,0x3f1d3f5cbecfbf75,0xbf393f183f5fbec4,0xbea13f673f09bf46,
0xbe603f713ee6bf55,0x3e893f7dbcc9bf7f,0xbf6f3e793f7e8000,0xbf273f2c3f51bef1,0x3f7cbd49bf7fbe48,0x3f4abf04bf6a3e95,0x3f313f4ebefcbf6d,0x3f733edbbf58bf22,
0xbeac3f623f18bf35,0x3e793f7f3d49bf7b,0x3f3e3f46bf04bf6d,0x3f7d3e95bf67bf0e,0xbedbbf753e163f80,0xbf5cbf223f2c3f55,0xbf80bdc93f783ec4,0xbf4e3ef13f71be48,
0x3f713ef1bf4ebf35,0x3f78bdc9bf80be48,0x3f2cbf22bf5c3ec4,0x3e16bf75bedb3f55,0xbf673e953f7d8000,0xbf043f463f3ebf0e,0x3d493f7f3e79bf6d,0x3f183f62beacbf7b,
0x3f7f3e79bf6abf0e,0x3f51bedbbf773dc9,0x3dfb3f803e60bf6d,0x3f393f4ebee6bf75,0xbf733e163f803e48,0xbf093f3e3f4abef1,0xbefcbf713e2f3f80,0xbf6fbf043f423f46,
0x3d97bf78becf3f55,0xbf13bf673e893f7f,0x3f7e3d49bf7abec4,0x3f31bf18bf653e95,0x3ea13f7d3cc9bf7b,0x3f583f2cbf1dbf62,0xbf5f3eac3f7c8000,0xbeb83f5c3f27bf22,
0xbf0ebf6d3e483f80,0xbf7bbec43f553f35,0xbf553ec43f7b0000,0xbe483f6d3f0ebf35,0x3f0e3f6dbe48bf80,0x3f7b3ec4bf55bf35,0x3f55bec4bf7b0000,0x3e48bf6dbf0e3f35,
0xbf553ec43f7b8000,0xbe483f6d3f0ebf35,0x3f0e3f6dbe48bf80,0x3f7b3ec4bf55bf35,0x3f55bec4bf7b8000,0x3e48bf6dbf0e3f35,0xbf0ebf6d3e483f80,0xbf7bbec43f553f35,
0xbf273f183f6abe48,0x3e2f3f803e89bf62,0xbf1dbf673e603f80,0xbf80be793f653f22,0x3ea1bf5cbf313f0e,0xbf09bf713dfb3f7f,0x3f5f3f2cbf13bf6d,0x3f6fbe16bf7fbe95,
0x3f423f4ebecfbf7b,0x3f7c3d49bf77bef1,0xbf4a3edb3f7a8000,0xbcc93f783ee6bf46,0xbf73bf043f393f55,0xbf583eac3f7e3dc9,0x3efcbf3ebf513ec4,0xbeb8bf7dbd973f75,
0x3f803e95bf5cbf35,0x3f18bf22bf673e48,0xbeacbf7fbe163f6d,0xbf78bef13f3e3f55,0xbf2cbf623e793f80,0xbf7dbdc93f713f0e,0xbedb3f463f4ebec4,0x3f043f75bd49bf7b,
0x3d49bf75bf043f35,0xbf4ebf463edb3f7b,0xbf713dc93f7d3ec4,0xbe793f623f2cbf0e,0xbf3e3ef13f788000,0x3e163f7f3eacbf55,0x3f673f22bf18bf6d,0x3f5cbe95bf80be48,
0xbf58bf3e3ee63f7b,0xbf5f3e793f803e95,0x3f6abe16bf7ebec4,0x3d97bf71bf133f22,0xbe2f3f673f27bf0e,0x3f4a3f4ebeb8bf7f,0xbf39bf5c3e893f80,0xbf733d493f7a3ef1,
0xbf093f2c3f65be48,0x3efc3f783cc9bf75,0xbecfbf7dbdfb3f6d,0xbf7fbeac3f513f46,0x3f7c3edbbf42bf55,0x3f1dbf18bf6f3dc9,0xbf313f043f778000,0x3ea13f803e60bf62,
0xbf46bf553e953f80,0xbf623e483f7f3ec4,0x3dc93f7b3ef1bf35,0x3f753f0ebf22bf6d,0x3f22bf0ebf750000,0xbef1bf7bbdc93f6d,0xbf7fbe483f623f35,0xbe953f553f46bec4,
0xbf223f0e3f758000,0x3ef13f7b3dc9bf6d,0x3f7f3e48bf62bf35,0x3e95bf55bf463ec4,0xbf46bf553e953f80,0xbf623e483f7f3ec4,0x3dc93f7b3ef1bf35,0x3f753f0ebf22bf6d,
0x3eb83f803e89bf55,0x3f7f3e79bf58bf46,0xbf51bf4e3ea13f80,0xbf4a3eac3f803e95,0xbf393edb3f7e3e48,0x3ee63f7d3e2fbf62,0x3e60bf5cbf423ec4,0xbf5fbf3e3ecf3f7f,
0x3f6fbd49bf77bf0e,0xbd97bf78bf093f22,0xbf133f183f738000,0x3f1d3f71bcc9bf75,0x3f313f67bdfbbf7b,0x3f65be16bf7cbef1,0xbf7abf043f273f6d,0xbefc3f2c3f6abdc9,
0xbe79bf7fbedb3f35,0xbf80be953f4e3f55,0xbe163f623f3ebec4,0x3f713f22bf04bf7b,0xbf5cbf463eac3f80,0xbf2c3ef13f7d3e48,0x3f183f753d49bf6d,0x3f67bdc9bf78bf0e,
0xbf78bdc93f673f35,0x3d493f753f18bf0e,0x3f7d3ef1bf2cbf6d,0x3eacbf46bf5c3e48,0xbf043f223f718000,0x3f3e3f62be16bf7b,0x3f4ebe95bf80bec4,0xbedbbf7fbe793f55,
0x3efc3f7d3e60bf55,0x3f6abd49bf73bf22,0xbf27bf71bcc93f6d,0xbf513e793f7e3ef1,0x3f4a3f5cbe2fbf7b,0x3f31bedbbf7fbe95,0xbf65bf3e3eb83f80,0xbf093f183f773dc9,
0x3f5fbe16bf7abf0e,0xbecfbf80bea13f46,0xbf423eac3f803ec4,0x3f133f783dfbbf62,0x3f1dbf04bf7cbe48,0xbf39bf673d973f75,0xbee63f2c3f6f8000,0x3f583f4ebe89bf7f,
0xbf6dbf353ec43f80,0xbec43f353f6d0000,0x3f6d3f35bec4bf80,0x3ec4bf35bf6d0000,0xbf6dbf353ec43f80,0xbec43f353f6d0000,0x3f6d3f35bec4bf80,0x3ec4bf35bf6d0000,
0xbec43f353f6d8000,0x3f6d3f35bec4bf80,0x3ec4bf35bf6d8000,0xbf6dbf353ec43f80,0xbec43f353f6d8000,0x3f6d3f35bec4bf80,0x3ec4bf35bf6d8000,0xbf6dbf353ec43f80,
0x3f7e3f04bf13bf7b,0x3cc9bf67bf423e95,0xbf73bf2c3ecf3f80,0xbe603f4e3f5fbdc9,0x3f773e16bf58bf55,0xbeb8bf80bee63f22,0xbf7fbeac3f393f6d,0x3e2f3f783f1dbef1,
0x3dfbbf5cbf513e48,0xbf80bedb3f273f75,0xbea13f3e3f6a8000,0x3f7a3f18befcbf7f,0xbe89bf7dbf093f0e,0xbf6fbd493f653f46,0x3d973f713f31bec4,0x3f7c3e79bf4abf62,
0xbf5c3dc93f713f35,0x3f2c3f753e16bf55,0x3f18bef1bf80bec4,0xbf67bf463e793f7b,0xbf78bf223edb3f80,0xbd493f623f4ebe48,0x3f7d3e95bf3ebf6d,0xbeacbf7fbf043f0e,
0x3f043f7f3eacbf35,0x3f3ebe95bf7dbf0e,0xbf4ebf623d493f6d,0xbedb3f223f783e48,0xbe793f463f678000,0x3f803ef1bf18bf7b,0xbe16bf75bf2c3ec4,0xbf71bdc93f5c3f55,
0xbcc9bf67bf4a3e48,0xbf73be163f513f62,0xbf093f043f7f3ec4,0x3f773f2cbeb8bf7f,0x3f6a3d49bf5fbf55,0xbf27bf78be603f46,0xbf7cbf183ee63f80,0x3dfb3f713f39be95,
0xbf80bedb3f1d3f7b,0x3ea13f7d3f13bef1,0x3f583f5cbd97bf6d,0x3e89bf3ebf6fbdc9,0xbecfbf80befc3f0e,0xbf423e793f7a3f22,0xbe2f3f4e3f658000,0x3f7e3eacbf31bf75,
0xbf7fbf0e3ef13f80,0x3e953f7b3f22bec4,0x3f46be48bf75bf35,0xbf62bf553dc93f6d,0xbdc93f553f620000,0x3f753e48bf46bf6d,0xbf22bf7bbe953f35,0xbef13f0e3f7f3ec4,
0xbdc93f553f628000,0x3f753e48bf46bf6d,0xbf22bf7bbe953f35,0xbef13f0e3f7f3ec4,0x3f7f3f0ebef1bf80,0xbe95bf7bbf223ec4,0xbf463e483f753f35,0x3f623f55bdc9bf6d,
0x3f13bedbbf7fbf0e,0xbf7ebf183ecf3f7f,0xbf80bf043efc3f80,0x3ee63f803f09bef1,0xbf7abf2c3ea13f7b,0x3e893f783f31be95,0x3eb83f7d3f1dbec4,0x3f27beacbf7cbf22,
0xbf51bf67bd973f55,0xbdfb3f4e3f6a3dc9,0xbcc93f5c3f5f8000,0x3f653d49bf58bf62,0xbe603f3e3f733e48,0x3f773e79bf39bf75,0x3f6f3e16bf4abf6d,0xbf42bf71be2f3f46,
0x3f3e3f753e79bf35,0x3e16bf46bf71be48,0xbf67bdc93f4e3f6d,0x3f5c3f623d49bf55,0xbf80bef13f043f80,0x3f183f7f3edbbf0e,0x3eacbf22bf7dbec4,0xbf78be953f2c3f7b,
0x3f2cbe95bf78bf35,0xbf7dbf223eac3f7b,0x3edb3f7f3f18bec4,0x3f04bef1bf80bf0e,0x3d493f623f5c8000,0x3f4ebdc9bf67bf55,0xbf71bf463e163f6d,0x3e793f753f3ebe48,
0xbee63f043f803f0e,0x3f7a3eacbf1dbf7f,0x3f773f3ebe2fbf6d,0xbecfbf7dbf273e95,0x3d97bf4ebf6fbe48,0xbf513d493f5f3f62,0xbf7ebedb3f093f80,0x3f393f783ea1bf22,
0x3f653f5c3cc9bf55,0xbe60bf71bf4a3dc9,0x3e89bf2cbf7cbec4,0xbf6abe163f423f75,0xbf7fbf183eb83f7b,0x3f133f803efcbef1,0x3dfb3f673f588000,0x3f31be79bf73bf46,
0xbf7bbec43f0e3f80,0x3f553f6d3e48bf35,0xbe48bf6dbf550000,0xbf0e3ec43f7b3f35,0x3f7b3ec4bf0ebf80,0xbf55bf6dbe483f35,0x3e483f6d3f550000,0x3f0ebec4bf7bbf35,
0x3e483f6d3f558000,0x3f0ebec4bf7bbf35,0xbf7bbec43f0e3f80,0x3f553f6d3e48bf35,0xbe48bf6dbf558000,0xbf0e3ec43f7b3f35,0x3f7b3ec4bf0ebf80,0xbf55bf6dbe483f35,
0xbee6bf7dbf313e48,0xbe603f2c3f7e3ef1,0xbf77beac3f133f80,0x3f6a3f5c3d97bf46,0x3f423f783eb8bf0e,0xbe2fbf67bf5fbdc9,0x3f4abd49bf58bf6d,0xbf80bf183ea13f75,
0xbf65be163f393f7b,0x3f7a3f3ebdfbbf62,0x3e893f713f518000,0x3ecfbf04bf7fbf22,0x3f27be79bf6fbf55,0xbf7cbedb3efc3f7f,0xbf1dbf80bf093ec4,0xbcc93f4e3f733e95,
0x3edbbef1bf7dbf35,0xbf5cbdc93f3e3f7b,0x3f803f22be79bf6d,0xbf4ebf75beac3f0e,0xbf71be953f183f80,0x3f783f46bd49bf55,0xbf2cbf7fbf043ec4,0x3e163f623f673e48,
0xbf67bf62be163f35,0x3f043f7f3f2cbe48,0x3d49bf46bf78bec4,0xbf183e953f713f55,0x3eac3f753f4e8000,0x3e79bf22bf80bf0e,0xbf3e3dc93f5c3f6d,0x3f7d3ef1bedbbf7b,
0x3f513d49bf42bf7b,0xbf7ebf043eb83f75,0xbcc9bf4ebf77bec4,0xbee63edb3f7a3f46,0xbf58bf71bea13f0e,0x3efc3f7d3f39bdc9,0xbf6abe793f1d3f80,0x3f7f3f2cbe2fbf62,
0xbf13bf80bf273e48,0x3dfb3f5c3f6f3e95,0xbf80bf183e893f6d,0x3f653f673e60bf22,0xbf093eac3f733f55,0x3f5f3e16bf31bf7f,0x3ecf3f783f4a8000,0x3d97bf3ebf7cbef1,
0xbf62be483f223f80,0x3f7f3f0ebe95bf6d,0xbf75bf55bdc93f35,0x3f463f7b3ef1bec4,0xbef1bf7bbf460000,0x3dc93f553f753ec4,0x3e95bf0ebf7fbf35,0xbf223e483f623f6d,
0x3ef13f7b3f468000,0xbdc9bf55bf75bec4,0xbe953f0e3f7f3f35,0x3f22be48bf62bf6d,0xbf62be483f223f80,0x3f7f3f0ebe95bf6d,0xbf75bf55bdc93f35,0x3f463f7b3ef1bec4,
0xbf80bf2c3dfb3f55,0x3f733f5c3e2fbf22,0xbf58be163f273f80,0x3f773edbbecfbf75,0xbeb8bf71bf5fbe48,0x3d973f4e3f7a3ef1,0xbf51bf78bee63ec4,0x3f1d3f803f31bdc9,
0xbcc93f3e3f7e3f0e,0x3ea1bf04bf7cbf46,0x3f093f7d3f428000,0xbe89bf67bf6abe95,0xbf6fbeac3efc3f7b,0x3f7f3f18be60bf62,0xbf133e793f653f6d,0x3f4a3d49bf39bf7f,
0xbf7dbf46bd493f35,0x3f713f623e79bf0e,0xbf5cbf75bedb3ec4,0x3f3e3f7f3f18be48,0xbf4ebdc93f2c3f80,0x3f673e95bf04bf7b,0xbf78bef13eac3f6d,0x3f803f22be16bf55,
0xbe163f223f803f35,0x3eacbef1bf78bf55,0xbf043e953f673f6d,0x3f2cbdc9bf4ebf7b,0x3f183f7f3f3e8000,0xbedbbf75bf5cbe48,0x3e793f623f713ec4,0xbd49bf46bf7dbf0e,
0xbf7ebf183e2f3f55,0x3f803f2cbd97bf46,0xbf73bedb3eb83f6d,0x3f7a3f04be89bf62,0xbf5fbe793f093f7b,0x3f6a3eacbee6bf75,0xbf42bd493f313f80,0x3f513e16bf1dbf7f,
0x3dfb3f4e3f7c3f0e,0xbcc9bf3ebf7fbf22,0x3ea13f673f6f3ec4,0xbe60bf5cbf77bef1,0x3efc3f783f583e48,0xbecfbf71bf65be95,0x3f273f803f398000,0xbf13bf7dbf4abdc9,
0x3f350000bf353f80,0xbf3500003f35bf80,0x3f350000bf353f80,0xbf3500003f35bf80,0x3f350000bf353f80,0xbf3500003f35bf80,0x3f350000bf353f80,0xbf3500003f35bf80,
0xbf353f80bf358000,0x3f35bf803f358000,0xbf353f80bf358000,0x3f35bf803f358000,0xbf353f80bf358000,0x3f35bf803f358000,0xbf353f80bf358000,0x3f35bf803f358000,
0xbf5fbf043f583f0e,0xbf6abedb3f653ef1,0xbf42bf2c3f393f35,0xbf51bf183f4a3f22,0xbf7ebe163f7c3e48,0xbf80bd493f7f3dc9,0xbf73beac3f6f3ec4,0xbf7abe793f773e95,
0xbefc3f5c3f09bf55,0xbecf3f673ee6bf62,0xbf273f3e3f31bf35,0xbf133f4e3f1dbf46,0xbdfb3f7d3e2fbf7b,0xbcc93f803d97bf7f,0xbea13f713eb8bf6d,0xbe603f783e89bf75,
0xbf183f463f2cbf35,0xbedb3f623f04bf55,0xbe793f753eacbf6d,0xbd493f7f3e16bf7b,0xbf7d3dc93f800000,0xbf713e953f78be48,0xbf5c3ef13f67bec4,0xbf3e3f223f4ebf0e,
0x3f4e3f22bf3ebf35,0x3f673ef1bf5cbf0e,0x3f783e95bf71bec4,0x3f803dc9bf7dbe48,0x3e163f7fbd49bf80,0x3eac3f75be79bf7b,0x3f043f62bedbbf6d,0x3f2c3f46bf18bf55,
0x3f6f3edbbf5fbf0e,0x3f7f3e16bf7abe95,0x3f133f5cbee6bf6d,0x3f4a3f2cbf31bf46,0x3cc93f803dfbbf7b,0x3ea13f78be2fbf7f,0xbf093f4e3f27bf35,0xbe893f713ecfbf62,
0x3eb8bf67befc3f55,0x3d97bf7dbe603f75,0x3f51bf04bf653ec4,0x3f1dbf3ebf393f22,0x3f803d49bf7ebe48,0x3f73be79bf7c3dc9,0x3f583f18bf42bf35,0x3f773eacbf6abef1,
0x3e953f7bbdc9bf80,0x3f223f55bef1bf6d,0x3f623f0ebf46bf35,0x3f7f3e48bf75bec4,0x3f75be48bf7f0000,0x3f46bf0ebf623ec4,0x3ef1bf55bf223f35,0x3dc9bf7bbe953f6d,
0x3f75be48bf7f8000,0x3f46bf0ebf623ec4,0x3ef1bf55bf223f35,0x3dc9bf7bbe953f6d,0xbe95bf7b3dc93f80,0xbf22bf553ef13f6d,0xbf62bf0e3f463f35,0xbf7fbe483f753ec4,
0x3f58bedbbf733e48,0x3efcbf4ebf313f22,0x3f6a3f04bf4abf35,0x3f7f3d49bf7cbe95,0xbf51bf2c3f273f55,0xbf7ebe793f6f3ef1,0x3cc9bf7dbe893f6d,0xbee6bf713e603f7f,
0xbf09bf673ea13f7b,0xbf5fbf183f393f46,0x3ecfbf5cbf1d3f35,0xbd97bf80be2f3f75,0xbf133f3e3f42bf0e,0xbdfb3f783eb8bf62,0xbf80be163f773ec4,0xbf653eac3f7abdc9,
0xbf71bef13f4e3f35,0xbf783dc93f803e48,0xbf2c3f223f5cbec4,0xbe163f753edbbf55,0x3f67be95bf7d0000,0x3f04bf46bf3e3f0e,0xbd49bf7fbe793f6d,0xbf18bf623eac3f7b,
0xbeac3f623f18bf35,0x3e793f7f3d49bf7b,0x3f3e3f46bf04bf6d,0x3f7d3e95bf67bf0e,0xbedbbf753e163f80,0xbf5cbf223f2c3f55,0xbf80bdc93f783ec4,0xbf4e3ef13f71be48,
0x3f273f5cbeb8bf7b,0x3f7c3eacbf5fbf22,0xbf1d3f2c3f58bec4,0x3cc93f7d3ea1bf62,0xbf65bf183f313f55,0xbf7a3d493f7e3e95,0x3e89bf67bf133f35,0xbecfbf783d973f7f,
0x3f42bf04bf6f3e48,0x3e2fbf71befc3f46,0x3f4a3f3ebf09bf6d,0x3f803e16bf73bef1,0xbee63f4e3f39bf0e,0x3e603f803dfbbf75,0xbf77bedb3f513f35,0xbf6a3e793f7f3dc9,
0xbf0ebf6d3e483f80,0xbf7bbec43f553f35,0xbf553ec43f7b0000,0xbe483f6d3f0ebf35,0x3f0e3f6dbe48bf80,0x3f7b3ec4bf55bf35,0x3f55bec4bf7b0000,0x3e48bf6dbf0e3f35,
0xbf553ec43f7b8000,0xbe483f6d3f0ebf35,0x3f0e3f6dbe48bf80,0x3f7b3ec4bf55bf35,0x3f55bec4bf7b8000,0x3e48bf6dbf0e3f35,0xbf0ebf6d3e483f80,0xbf7bbec43f553f35,
0x3d973f7d3eb8bf55,0x3f513f3ebefcbf75,0xbf7ebeac3f583f35,0xbf393f043f73bdc9,0xbee6bf783cc93f7b,0xbf7abedb3f4a3f46,0x3f77bd49bf7cbec4,0x3ecfbf4ebf423ef1,
0x3f7f3e16bf6fbf0e,0x3f13bf2cbf5f3e95,0xbdfb3f713f09bf35,0x3f313f5cbea1bf7f,0xbf653e793f803e48,0xbe603f673f1dbf22,0xbe89bf80be2f3f6d,0xbf6abf183f273f62,
0x3d49bf75bf043f35,0xbf4ebf463edb3f7b,0xbf713dc93f7d3ec4,0xbe793f623f2cbf0e,0xbf3e3ef13f780000,0x3e163f7f3eacbf55,0x3f673f22bf18bf6d,0x3f5cbe95bf80be48,
0xbf80be953f5c3f35,0xbf183f223f67be48,0x3eac3f7f3e16bf6d,0x3f783ef1bf3ebf55,0x3f2c3f62be79bf80,0x3f7d3dc9bf71bf0e,0x3edbbf46bf4e3ec4,0xbf04bf753d493f7b,
0x3e603f803ea1bf55,0x3f773f04bf31bf62,0xbf6fbf183f1d3f6d,0xbf423edb3f7c3dc9,0x3f51beacbf7fbe48,0xbdfbbf7dbecf3f46,0x3cc93f783efcbf35,0x3f653f2cbf09bf75,
0x3f7a3d49bf73bf0e,0x3e89bf5cbf393ef1,0xbeb83f4e3f4abec4,0x3f273f67be2fbf7f,0xbf13bf713d973f7b,0xbf7ebe163f6a3f22,0x3f803e79bf5fbf35,0x3ee6bf3ebf583e95,
0x3f463f55be95bf80,0x3f62be48bf7fbec4,0xbdc9bf7bbef13f35,0xbf75bf0e3f223f6d,0xbf223f0e3f750000,0x3ef13f7b3dc9bf6d,0x3f7f3e48bf62bf35,0x3e95bf55bf463ec4,
0x3f22bf0ebf758000,0xbef1bf7bbdc93f6d,0xbf7fbe483f623f35,0xbe953f553f46bec4,0x3f463f55be95bf80,0x3f62be48bf7fbec4,0xbdc9bf7bbef13f35,0xbf75bf0e3f223f6d,
0xbf6abf2c3efc3f7b,0xbf273f043f7a3dc9,0x3f7c3e16bf65bf35,0x3dfbbf67bf313ef1,0x3cc9bf71bf1d3f0e,0xbf73bf183f133f75,0x3f093f783d97bf6d,0x3f773d49bf6fbf22,
0xbecf3f3e3f5fbe48,0x3f423f5cbe60bf7f,0xbe2fbf7dbee63f35,0xbf7ebedb3f393f62,0xbf80beac3f4a3f55,0xbea13f4e3f51be95,0x3f58be79bf7fbec4,0xbe89bf80beb83f46,
0x3f783dc9bf67bf35,0xbd49bf75bf183f0e,0xbf7dbef13f2c3f6d,0xbeac3f463f5cbe48,0x3f04bf22bf710000,0xbf3ebf623e163f7b,0xbf4e3e953f803ec4,0x3edb3f7f3e79bf55,
0xbe79bf7fbedb3f35,0xbf80be953f4e3f55,0xbe163f623f3ebec4,0x3f713f22bf04bf7b,0xbf5cbf463eac3f80,0xbf2c3ef13f7d3e48,0x3f183f753d49bf6d,0x3f67bdc9bf78bf0e,
0xbe893f4e3f58be48,0x3f6f3f2cbee6bf7f,0x3d97bf67bf393ec4,0xbf7cbf043f1d3f75,0x3dfb3f783f13bf0e,0x3f803eacbf42bf62,0xbea1bf80becf3f35,0xbf7abe163f5f3f46,
0x3f773f18bf09bf7b,0x3eb8bf3ebf653dc9,0xbf7fbedb3f313f6d,0xbe2f3f5c3f4abe95,0x3f7e3e79bf51bf55,0xbcc9bf71bf273ef1,0xbf73bd493f6a3f35,0x3e603f7d3efcbf22,
0xbf6dbf353ec43f80,0xbec43f353f6d0000,0x3f6d3f35bec4bf80,0x3ec4bf35bf6d0000,0xbf6dbf353ec43f80,0xbec43f353f6d0000,0x3f6d3f35bec4bf80,0x3ec4bf35bf6d0000,
0xbec43f353f6d8000,0x3f6d3f35bec4bf80,0x3ec4bf35bf6d8000,0xbf6dbf353ec43f80,0xbec43f353f6d8000,0x3f6d3f35bec4bf80,0x3ec4bf35bf6d8000,0xbf6dbf353ec43f80,
0x3f4abe79bf7cbf0e,0xbf31bf71bd973f62,0xbf653d493f6f3f35,0x3f093f7d3e89bf46,0x3efcbf18bf7abe48,0xbf6abf3e3ea13f7f,0xbf273edb3f803ec4,0x3f513f5cbdfbbf75,
0xbf1dbf78be2f3f55,0xbf393eac3f7f3ef1,0x3ee63f803eb8bf35,0x3f58be16bf77bf22,0xbf5fbf4e3e603f7b,0xbecf3f2c3f733dc9,0x3f423f67bcc9bf6d,0x3f13bf04bf7ebe95,
0x3f043f7f3eacbf35,0x3f3ebe95bf7dbf0e,0xbf4ebf623d493f6d,0xbedb3f223f783e48,0xbe793f463f670000,0x3f803ef1bf18bf7b,0xbe16bf75bf2c3ec4,0xbf71bdc93f5c3f55,
0x3f5cbdc9bf71bf35,0xbf2cbf75be163f55,0xbf183ef13f803ec4,0x3f673f46be79bf7b,0x3f783f22bedbbf80,0x3d49bf62bf4e3e48,0xbf7dbe953f3e3f6d,0x3eac3f7f3f04bf0e,
0xbf313eac3f7e3f0e,0x3f653f4ebe2fbf75,0x3f7a3e79bf42bf6d,0xbefcbf80becf3f22,0xbf6fbf3e3e893f7b,0xbd973f5c3f58bdc9,0x3f133f7d3ea1bf35,0x3f1dbedbbf80bef1,
0x3f393f713dfbbf55,0x3ee6bf18bf7cbe95,0xbe60bf78bf273ec4,0xbf5f3d493f6a3f46,0xbeb83f2c3f773e48,0x3f7f3f04bf09bf7f,0x3f51be16bf73bf35,0xbf4abf67bcc93f62,
0x3f7f3f0ebef1bf80,0xbe95bf7bbf223ec4,0xbf463e483f753f35,0x3f623f55bdc9bf6d,0x3dc9bf55bf620000,0xbf75be483f463f6d,0x3f223f7b3e95bf35,0x3ef1bf0ebf7fbec4,
0x3dc9bf55bf628000,0xbf75be483f463f6d,0x3f223f7b3e95bf35,0x3ef1bf0ebf7fbec4,0xbf7fbf0e3ef13f80,0x3e953f7b3f22bec4,0x3f46be48bf75bf35,0xbf62bf553dc93f6d,
0x3e2f3f713f42be48,0x3f4abe16bf6fbf46,0x3f39be79bf77bf35,0xbf73bf3e3e603f75,0x3f58bd49bf65bf55,0xbf5fbf5c3cc93f62,0xbf6abf4e3dfb3f6d,0x3d973f673f51bdc9,
0x3f7c3eacbf27bf7b,0xbf1dbf7dbeb83f22,0xbf31bf78be893f35,0xbea13f2c3f7a3e95,0xbf09bf80bee63f0e,0xbefc3f043f803ef1,0xbecf3f183f7e3ec4,0x3f7f3edbbf13bf7f,
0xbf2c3e953f783f35,0x3f7d3f22beacbf7b,0xbedbbf7fbf183ec4,0xbf043ef13f803f0e,0xbd49bf62bf5c0000,0xbf4e3dc93f673f55,0x3f713f46be16bf6d,0xbe79bf75bf3e3e48,
0x3f3e3f753e79bf35,0x3e16bf46bf71be48,0xbf67bdc93f4e3f6d,0x3f5c3f623d49bf55,0xbf80bef13f043f80,0x3f183f7f3edbbf0e,0x3eacbf22bf7dbec4,0xbf78be953f2c3f7b,
0xbf73be793f313f7b,0x3f583f673dfbbf46,0x3efc3f803f13bec4,0x3eb8bf18bf7fbef1,0x3f42be16bf6abf55,0xbf7cbf2c3e893f75,0xbf4abf71be603f35,0x3cc93f5c3f653dc9,
0x3ea13f783f39be48,0x3f09bedbbf7ebf22,0x3f5f3d49bf51bf6d,0xbf6fbf4e3d973f62,0xbf27bf7dbecf3f0e,0xbe2f3f3e3f773e95,0xbf1d3eac3f7a3f35,0x3f803f04bee6bf7f,
0xbf7bbec43f0e3f80,0x3f553f6d3e48bf35,0xbe48bf6dbf550000,0xbf0e3ec43f7b3f35,0x3f7b3ec4bf0ebf80,0xbf55bf6dbe483f35,0x3e483f6d3f550000,0x3f0ebec4bf7bbf35,
0x3e483f6d3f558000,0x3f0ebec4bf7bbf35,0xbf7bbec43f0e3f80,0x3f553f6d3e48bf35,0xbe48bf6dbf558000,0xbf0e3ec43f7b3f35,0x3f7b3ec4bf0ebf80,0xbf55bf6dbe483f35,
0xbf73bf4e3cc93f55,0x3f093f803f1dbe95,0xbefc3edb3f7c3f35,0x3f6f3e79bf27bf7f,0x3f7f3f04becfbf7b,0xbf51bf71be893f22,0x3dfbbf3ebf7abec4,0xbf393e163f653f62,
0xbea13f183f803f0e,0x3f583d49bf4abf75,0x3f5f3f673e2fbf35,0xbeb8bf78bf423dc9,0xbd97bf5cbf6abe48,0xbf133eac3f773f46,0xbf7ebf2c3e603f6d,0x3f313f7d3ee6bef1,
0xbf67bf62be163f35,0x3f043f7f3f2cbe48,0x3d49bf46bf78bec4,0xbf183e953f713f55,0x3eac3f753f4e0000,0x3e79bf22bf80bf0e,0xbf3e3dc93f5c3f6d,0x3f7d3ef1bedbbf7b,
0xbedb3ef13f7d3f35,0x3f5c3dc9bf3ebf7b,0xbf80bf223e793f6d,0x3f4e3f753eacbf0e,0x3f713e95bf18bf80,0xbf78bf463d493f55,0x3f2c3f7f3f04bec4,0xbe16bf62bf67be48,
0xbf7cbf3e3d973f55,0x3f4a3f783ecfbef1,0xbf313e163f5f3f6d,0x3f733eacbf09bf7f,0x3e603f673f653e48,0x3e89bf18bf80bf22,0x3f6f3f5c3dfbbf35,0xbf27bf80bf133e95,
0xbe2f3f2c3f7f3f0e,0x3f1dbe79bf6abf62,0x3f393f7d3efcbec4,0xbea1bf71bf58bdc9,0x3f7a3edbbee6bf7b,0xbf77bf4ebcc93f46,0x3eb8bf04bf7ebf35,0xbf423d493f513f75,
0x3f623e48bf22bf80,0xbf7fbf0e3e953f6d,0x3f753f553dc9bf35,0xbf46bf7bbef13ec4,0x3ef13f7b3f460000,0xbdc9bf55bf75bec4,0xbe953f0e3f7f3f35,0x3f22be48bf62bf6d,
0xbef1bf7bbf468000,0x3dc93f553f753ec4,0x3e95bf0ebf7fbf35,0xbf223e483f623f6d,0x3f623e48bf22bf80,0xbf7fbf0e3e953f6d,0x3f753f553dc9bf35,0xbf46bf7bbef13ec4,
0x3f39bd49bf4abf7b,0xbf65be793f133f7f,0x3e60bf18bf7fbf35,0xbefc3eac3f6f3f62,0x3f6a3f673e89bf0e,0xbf42bf7dbf093e95,0x3f7c3f04bea1bf6d,0xbf7ebf3e3cc93f46,
0xbf31bf80bf1d3e48,0x3ee63f783f513dc9,0xbf7abf4ebd973f35,0x3f5f3f713eb8bef1,0x3ecfbedbbf77bf55,0xbf273e163f583f75,0xbe2fbf5cbf73bec4,0xbdfb3f2c3f803f22,
0x3e16bf22bf80bf35,0xbeac3ef13f783f55,0x3f04be95bf67bf6d,0xbf2c3dc93f4e3f7b,0xbf18bf7fbf3e0000,0x3edb3f753f5c3e48,0xbe79bf62bf71bec4,0x3d493f463f7d3f0e,
0xbf7dbf46bd493f35,0x3f713f623e79bf0e,0xbf5cbf75bedb3ec4,0x3f3e3f7f3f18be48,0xbf4ebdc93f2c3f80,0x3f673e95bf04bf7b,0xbf78bef13eac3f6d,0x3f803f22be16bf55,
0xbf4abf7dbf133e48,0x3f393f803f27bdc9,0xbf65bf71becf3ec4,0x3f583f783efcbe95,0xbf77bf5cbe603f0e,0x3f6f3f673ea1bef1,0xbf7fbf3ebcc93f35,0x3f7c3f4e3dfbbf22,
0xbf1d3e163f513f7b,0x3f31bd49bf42bf7f,0xbee63eac3f6a3f6d,0x3f09be79bf5fbf75,0xbe893f043f7a3f55,0x3eb8bedbbf73bf62,0xbd973f2c3f803f35,0x3e2fbf18bf7ebf46,
0x3f003f003f003f00,0x3f003f003f003f00,0x3f003f003f003f00,0x3f003f003f003f00,0x3f003f003f003f00,0x3f003f003f003f00,0x3f003f003f003f00,0x3f003f003f003f00,
0xbf003f00bf003f00,0xbf003f00bf003f00,0xbf003f00bf003f00,0xbf003f00bf003f00,0xbf003f00bf003f00,0xbf003f00bf003f00,0xbf003f00bf003f00,0xbf003f00bf003f00,
0xbe89be79be60be48,0xbeb8beacbea1be95,0xbd97bd49bcc90000,0xbe2fbe16bdfbbdc9,0xbf1dbf18bf13bf0e,0xbf31bf2cbf27bf22,0xbee6bedbbecfbec4,0xbf09bf04befcbef1,
0xbf77bf78bf7abf7b,0xbf6fbf71bf73bf75,0xbf7fbf80bf80bf80,0xbf7cbf7dbf7ebf7f,0xbf4abf4ebf51bf55,0xbf39bf3ebf42bf46,0xbf65bf67bf6abf6d,0xbf58bf5cbf5fbf62,
0xbf18bf22bf2cbf35,0xbedbbef1bf04bf0e,0xbe79be95beacbec4,0xbd49bdc9be16be48,0xbf7dbf7fbf80bf80,0xbf71bf75bf78bf7b,0xbf5cbf62bf67bf6d,0xbf3ebf46bf4ebf55,
0x3f4e3f463f3e3f35,0x3f673f623f5c3f55,0x3f783f753f713f6d,0x3f803f7f3f7d3f7b,0x3e163dc93d498000,0x3eac3e953e793e48,0x3f043ef13edb3ec4,0x3f2c3f223f183f0e,
0x3f6a3f713f773f7b,0x3f423f4e3f583f62,0x3f7c3f783f733f6d,0x3f7e3f803f803f7f,0x3f393f2c3f1d3f0e,0x3f653f5c3f513f46,0x3e603e163d970000,0x3efc3edb3eb83e95,
0xbecfbeacbe89be48,0xbf27bf18bf09bef1,0x3e2f3e793ea13ec4,0xbdfbbd493cc93dc9,0x3f313f3e3f4a3f55,0x3ee63f043f133f22,0x3f7a3f7d3f7f3f80,0x3f5f3f673f6f3f75,
0x3f753f7b3f7f3f80,0x3f463f553f623f6d,0x3ef13f0e3f223f35,0x3dc93e483e953ec4,0xbe95be48bdc90000,0xbf22bf0ebef1bec4,0xbf62bf55bf46bf35,0xbf7fbf7bbf75bf6d,
0xbe95be48bdc98000,0xbf22bf0ebef1bec4,0xbf62bf55bf46bf35,0xbf7fbf7bbf75bf6d,0xbf75bf7bbf7fbf80,0xbf46bf55bf62bf6d,0xbef1bf0ebf22bf35,0xbdc9be48be95bec4,
0xbf7abf71bf65bf55,0xbf77bf7dbf80bf7f,0xbeb8be79bdfb0000,0xbf42bf2cbf13bef1,0x3e2f3d49bd97be48,0x3f1d3f043ecf3e95,0xbf39bf4ebf5fbf6d,0xbea1bedbbf09bf22,
0xbe60beacbee6bf0e,0x3e893e163cc9bdc9,0xbf6fbf78bf7ebf80,0xbf27bf3ebf51bf62,0x3f7c3f803f7f3f7b,0x3f4a3f5c3f6a3f75,0x3f313f183efc3ec4,0x3f733f673f583f46,
0x3f713f623f4e3f35,0x3f783f7f3f803f7b,0x3f2c3f463f5c3f6d,0x3e163e953edb3f0e,0xbf67bf75bf7dbf80,0xbf04bf22bf3ebf55,0x3d49bdc9be79bec4,0x3f183ef13eac3e48,
0x3eac3ef13f183f35,0xbe79bdc93d493e48,0xbf3ebf22bf04bec4,0xbf7dbf75bf67bf55,0x3edb3e953e168000,0x3f5c3f463f2c3f0e,0x3f803f7f3f783f6d,0x3f4e3f623f713f7b,
0xbf7fbf78bf6abf55,0xbf51bf67bf77bf7f,0xbdfb3d493e603ec4,0xbf39bf18bee6be95,0x3f733f7d3f803f7b,0x3f093f2c3f4a3f62,0x3efc3eac3e2f0000,0x3f6f3f5c3f423f22,
0xbd97be79becfbf0e,0x3f133edb3e893dc9,0xbf7ebf80bf7abf6d,0xbf31bf4ebf65bf75,0xbea1be163cc93e48,0xbf58bf3ebf1dbef1,0x3f5f3f713f7c3f80,0x3eb83f043f273f46,
0x3f553f6d3f7b3f80,0x3e483ec43f0e3f35,0xbf0ebec4be480000,0xbf7bbf6dbf55bf35,0xbf55bf6dbf7bbf80,0xbe48bec4bf0ebf35,0x3f0e3ec43e480000,0x3f7b3f6d3f553f35,
0xbf0ebec4be488000,0xbf7bbf6dbf55bf35,0xbf55bf6dbf7bbf80,0xbe48bec4bf0ebf35,0x3f0e3ec43e488000,0x3f7b3f6d3f553f35,0x3f553f6d3f7b3f80,0x3e483ec43f0e3f35,
0xbf27bf4ebf6abf7b,0x3e2fbd49be89bef1,0xbf1dbedbbe600000,0xbf80bf78bf65bf46,0x3ea13f043f313f55,0xbf09beacbdfb3dc9,0x3f5f3f3e3f133ec4,0x3f6f3f7d3f7f3f75,
0x3f423f183ecf3e48,0x3f7c3f803f773f62,0xbf4abf67bf7abf80,0xbcc9be79bee6bf22,0xbf73bf5cbf39bf0e,0xbf58bf71bf7ebf7f,0x3efc3f2c3f513f6d,0xbeb8be163d973e95,
0x3d493e953f043f35,0xbf4ebf22bedbbe48,0xbf71bf7fbf7dbf6d,0xbe79bef1bf2cbf55,0xbf3ebf62bf78bf80,0x3e16bdc9beacbf0e,0x3f673f463f183ec4,0x3f5c3f753f803f7b,
0xbf80bf75bf5cbf35,0xbf18bf46bf67bf7b,0x3eac3dc9be16bec4,0x3f783f623f3e3f0e,0x3f2c3ef13e798000,0x3f7d3f7f3f713f55,0x3edb3f223f4e3f6d,0xbf04be95bd493e48,
0x3f583f2c3ee63e48,0x3f5f3f783f803f75,0xbf6abf7dbf7ebf6d,0xbd97beacbf13bf46,0x3e2f3edb3f273f55,0xbf4abf18beb8bdc9,0x3f393f043e890000,0x3f733f803f7a3f62,
0x3f093f3e3f653f7b,0xbefcbe793cc93e95,0x3ecf3e16bdfbbec4,0x3f7f3f713f513f22,0xbf7cbf67bf42bf0e,0xbf1dbf4ebf6fbf7f,0x3f313f5c3f773f80,0xbea1bd493e603ef1,
0x3f223f553f753f80,0xbef1be483dc93ec4,0xbf7fbf7bbf62bf35,0xbe95bf0ebf46bf6d,0x3f463f0e3e950000,0x3f623f7b3f7f3f6d,0xbdc93e483ef13f35,0xbf75bf55bf22bec4,
0xbf46bf0ebe958000,0xbf62bf7bbf7fbf6d,0x3dc9be48bef1bf35,0x3f753f553f223ec4,0x3f223f553f753f80,0xbef1be483dc93ec4,0xbf7fbf7bbf62bf35,0xbe95bf0ebf46bf6d,
0x3eb83d49be89bf0e,0x3f7f3f783f583f22,0xbf51bf18bea10000,0xbf4abf71bf80bf75,0xbf39bf67bf7ebf7b,0x3ee63e16be2fbef1,0x3e603f043f423f6d,0xbf5fbf2cbecfbdc9,
0x3f6f3f803f773f55,0xbd973e793f093f46,0xbf13bf4ebf73bf80,0x3f1d3eac3cc9be95,0x3f313edb3dfbbe48,0x3f653f7d3f7c3f62,0xbf7abf5cbf27bec4,0xbefcbf3ebf6abf7f,
0xbf78bf7fbf67bf35,0x3d49be95bf18bf55,0x3f7d3f623f2c3ec4,0x3eac3f223f5c3f7b,0xbf04bf46bf71bf80,0x3f3e3ef13e16be48,0x3f4e3f753f803f6d,0xbedbbdc93e793f0e,
0x3e79bdc9bedbbf35,0x3f803f753f4e3f0e,0x3e163ef13f3e3f6d,0xbf71bf46bf04be48,0x3f5c3f223eac8000,0x3f2c3f623f7d3f7b,0xbf18be953d493ec4,0xbf67bf7fbf78bf55,
0xbefcbe163e603f0e,0xbf6abf80bf73bf46,0x3f273eacbcc9bec4,0x3f513f783f7e3f62,0xbf4abf04be2f3e48,0xbf31bf67bf7fbf75,0x3f653f2c3eb80000,0x3f093f4e3f773f7f,
0xbf5fbf7dbf7abf55,0x3ecf3d49bea1bf22,0x3f423f713f803f6d,0xbf13be793dfb3ef1,0xbf1dbf5cbf7cbf7b,0x3f393edb3d97be95,0x3ee63f3e3f6f3f80,0xbf58bf18be893dc9,
0x3ec43f353f6d3f80,0xbf6dbf35bec40000,0xbec4bf35bf6dbf80,0x3f6d3f353ec40000,0x3ec43f353f6d3f80,0xbf6dbf35bec40000,0xbec4bf35bf6dbf80,0x3f6d3f353ec40000,
0xbf6dbf35bec48000,0xbec4bf35bf6dbf80,0x3f6d3f353ec48000,0x3ec43f353f6d3f80,0xbf6dbf35bec48000,0xbec4bf35bf6dbf80,0x3f6d3f353ec48000,0x3ec43f353f6d3f80,
0x3f7e3f5c3f133e48,0x3cc93edb3f423f75,0xbf73bf3ebecf0000,0xbe60bf18bf5fbf7f,0x3f773f7d3f583f0e,0xbeb83d493ee63f46,0xbf7fbf71bf39bec4,0x3e2fbe79bf1dbf62,
0x3dfb3f043f513f7b,0xbf80bf67bf27be95,0xbea1bf2cbf6abf80,0x3f7a3f4e3efc3dc9,0xbe893e163f093f55,0xbf6fbf80bf65bf22,0x3d97beacbf31bf6d,0x3f7c3f783f4a3ef1,
0x3f043dc9beacbf35,0x3f3e3f753f7d3f55,0xbf4ebef1bd493ec4,0xbedbbf46bf78bf7b,0xbe79bf22bf67bf80,0x3f803f623f183e48,0xbe163e953f2c3f6d,0xbf71bf7fbf5cbf0e,
0x3f5c3f7f3f713f35,0xbf2cbe953e163f0e,0xbf18bf62bf80bf6d,0x3f673f223e79be48,0x3f783f463edb8000,0x3d493ef13f4e3f7b,0xbf7dbf75bf3ebec4,0x3eacbdc9bf04bf55,
0x3cc9bedbbf4abf7b,0x3f733f7d3f513ef1,0x3f093f5c3f7f3f6d,0xbf77bf3ebeb83dc9,0xbf6abf80bf5fbf0e,0x3f273e79be60bf22,0x3f7c3f4e3ee60000,0xbdfb3eac3f393f75,
0x3f803f673f1d3e48,0xbea13e163f133f62,0xbf58bf04bd973ec4,0xbe89bf2cbf6fbf7f,0x3ecfbd49befcbf55,0x3f423f783f7a3f46,0x3e2f3f183f653f80,0xbf7ebf71bf31be95,
0x3dc93f0e3f623f80,0xbf75bf7bbf46bec4,0x3f223e48be95bf35,0x3ef13f553f7f3f6d,0xbf7fbf55bef10000,0x3e95be48bf22bf6d,0x3f463f7b3f753f35,0xbf62bf0ebdc93ec4,
0xbf7fbf55bef18000,0x3e95be48bf22bf6d,0x3f463f7b3f753f35,0xbf62bf0ebdc93ec4,0xbdc9bf0ebf62bf80,0x3f753f7b3f463ec4,0xbf22be483e953f35,0xbef1bf55bf7fbf6d,
0x3f133f673f7f3f55,0xbf7ebf4ebecf3dc9,0xbf80bf5cbefc0000,0x3ee6bd49bf09bf62,0xbf7abf3ebea13e48,0x3e89be79bf31bf75,0x3eb8be16bf1dbf6d,0x3f273f713f7c3f46,
0xbf51bedb3d973f0e,0xbdfbbf18bf6abf7f,0xbcc9bf04bf5fbf80,0x3f653f803f583ef1,0xbe60bf2cbf73bf7b,0x3f773f783f393e95,0x3f6f3f7d3f4a3ec4,0xbf42beac3e2f3f22,
0x3f2c3f753f783f35,0xbf7dbf46beac3e48,0x3edbbdc9bf18bf6d,0x3f043f623f803f55,0x3d49bef1bf5cbf80,0x3f4e3f7f3f673f0e,0xbf71bf22be163ec4,0x3e79be95bf3ebf7b,
0xbf3ebe953e793f35,0xbe16bf22bf71bf7b,0x3f673f7f3f4e3ec4,0xbf5cbef13d493f0e,0x3f803f623f048000,0xbf18bdc93edb3f55,0xbeacbf46bf7dbf6d,0x3f783f753f2c3e48,
0x3ee63f5c3f803f55,0xbf7abf71bf1dbdc9,0xbf77bf2cbe2f3ec4,0x3ecfbe16bf27bf75,0xbd97bf18bf6fbf7b,0x3f513f803f5f3ef1,0x3f7e3f673f090000,0xbf39be793ea13f46,
0xbf65bf043cc93f0e,0x3e60beacbf4abf7f,0xbe89bf3ebf7cbf6d,0x3f6a3f7d3f423e95,0x3f7f3f4e3eb8be48,0xbf13bd493efc3f62,0xbdfb3edb3f583f80,0xbf31bf78bf73bf22,
0xbe483ec43f553f80,0xbf0ebf6dbf7bbf35,0x3f7b3f6d3f0e0000,0xbf55bec43e483f35,0x3e48bec4bf55bf80,0x3f0e3f6d3f7b3f35,0xbf7bbf6dbf0e0000,0x3f553ec4be48bf35,
0xbf7bbf6dbf0e8000,0x3f553ec4be48bf35,0xbe483ec43f553f80,0xbf0ebf6dbf7bbf35,0x3f7b3f6d3f0e8000,0xbf55bec43e483f35,0x3e48bec4bf55bf80,0x3f0e3f6d3f7b3f35,
0xbee63e163f313f7b,0xbe60bf3ebf7ebf62,0xbf77bf71bf130000,0x3f6a3f04bd97bf22,0x3f423e79beb8bf55,0xbe2f3edb3f5f3f7f,0x3f4a3f803f583ec4,0xbf80bf4ebea13e95,
0xbf65bf7dbf39be48,0x3f7a3f2c3dfbbef1,0x3e89beacbf51bf80,0x3ecf3f5c3f7f3f46,0x3f273f783f6f3f0e,0xbf7cbf67befc3dc9,0xbf1dbd493f093f6d,0xbcc9bf18bf73bf75,
0xbf67bef13e163f35,0x3f04bdc9bf2cbf7b,0x3d493f223f783f6d,0xbf18bf75bf71bf0e,0x3eacbe95bf4ebf80,0x3e793f463f803f55,0xbf3ebf7fbf5cbec4,0x3f7d3f623edbbe48,
0xbedbbf62bf7dbf35,0x3f5c3f7f3f3e3e48,0xbf80bf46be793ec4,0x3f4e3e95beacbf55,0x3f713f753f188000,0xbf78bf22bd493f0e,0x3f2c3dc9bf04bf6d,0xbe163ef13f673f7b,
0xbf51bf80bf42be48,0x3f7e3f5c3eb8be95,0x3cc9bf18bf77bf6d,0x3ee63f673f7a3f22,0x3f583eacbea1bf55,0xbefc3e163f393f7f,0x3f6a3f783f1d0000,0xbf7fbf3ebe2f3ef1,
0x3f13bd49bf27bf7b,0xbdfb3f043f6f3f75,0x3f803f4e3e89bec4,0xbf65bedb3e603f46,0x3f093f713f733f0e,0xbf5fbf7dbf31bdc9,0xbecf3e793f4a3f80,0xbd97bf2cbf7cbf62,
0xbef13e483f463f80,0x3dc9bf0ebf75bf6d,0x3e953f553f7f3f35,0xbf22bf7bbf62bec4,0x3f623f7b3f220000,0xbf7fbf55be953ec4,0x3f753f0ebdc9bf35,0xbf46be483ef13f6d,
0xbf62bf7bbf228000,0x3f7f3f553e95bec4,0xbf75bf0e3dc93f35,0x3f463e48bef1bf6d,0xbef13e483f463f80,0x3dc9bf0ebf75bf6d,0x3e953f553f7f3f35,0xbf22bf7bbf62bec4,
0xbf80bf3ebdfb3f0e,0x3f733f04be2fbf46,0xbf58bf7dbf270000,0x3f773f673ecfbe95,0xbeb83eac3f5f3f7b,0x3d97bf18bf7abf62,0xbf51be793ee63f6d,0x3f1dbd49bf31bf7f,
0xbcc9bf2cbf7ebf55,0x3ea13f5c3f7c3f22,0x3f09be16bf42bf80,0xbe893edb3f6a3f75,0xbf6fbf71befc3e48,0x3f7f3f4e3e60bef1,0xbf13bf78bf65bec4,0x3f4a3f803f393dc9,
0xbe16bf46bf80bf35,0x3eac3f623f783f0e,0xbf04bf75bf67bec4,0x3f2c3f7f3f4e3e48,0x3f18bdc9bf3ebf80,0xbedb3e953f5c3f7b,0x3e79bef1bf71bf6d,0xbd493f223f7d3f55,
0x3f7d3f22bd49bf35,0xbf71bef13e793f55,0x3f5c3e95bedbbf6d,0xbf3ebdc93f183f7b,0x3f4e3f7f3f2c8000,0xbf67bf75bf043e48,0x3f783f623eacbec4,0xbf80bf46be163f0e,
0x3f7e3f4e3e2fbf0e,0xbf80bf3ebd973f22,0x3f733f673eb8bec4,0xbf7abf5cbe893ef1,0x3f5f3f783f09be48,0xbf6abf71bee63e95,0x3f423f803f310000,0xbf51bf7dbf1d3dc9,
0xbdfb3f183f7c3f55,0x3cc9bf2cbf7fbf46,0xbea13edb3f6f3f6d,0x3e60bf04bf77bf62,0xbefc3e793f583f7b,0x3ecfbeacbf65bf75,0xbf273d493f393f80,0x3f13be16bf4abf7f,
0x3f003f003f003f00,0x3f003f003f003f00,0x3f003f003f003f00,0x3f003f003f003f00,0x3f003f003f003f00,0x3f003f003f003f00,0x3f003f003f003f00,0x3f003f003f003f00,
0xbf003f00bf003f00,0xbf003f00bf003f00,0xbf003f00bf003f00,0xbf003f00bf003f00,0xbf003f00bf003f00,0xbf003f00bf003f00,0xbf003f00bf003f00,0xbf003f00bf003f00,
0xbf5fbf5cbf58bf55,0xbf6abf67bf65bf62,0xbf42bf3ebf39bf35,0xbf51bf4ebf4abf46,0xbf7ebf7dbf7cbf7b,0xbf80bf80bf7fbf7f,0xbf73bf71bf6fbf6d,0xbf7abf78bf77bf75,
0xbefcbf04bf09bf0e,0xbecfbedbbee6bef1,0xbf27bf2cbf31bf35,0xbf13bf18bf1dbf22,0xbdfbbe16be2fbe48,0xbcc9bd49bd97bdc9,0xbea1beacbeb8bec4,0xbe60be79be89be95,
0x3f4e3f463f3e3f35,0x3f673f623f5c3f55,0x3f783f753f713f6d,0x3f803f7f3f7d3f7b,0x3e163dc93d490000,0x3eac3e953e793e48,0x3f043ef13edb3ec4,0x3f2c3f223f183f0e,
0x3f183f223f2c3f35,0x3edb3ef13f043f0e,0x3e793e953eac3ec4,0x3d493dc93e163e48,0x3f7d3f7f3f803f80,0x3f713f753f783f7b,0x3f5c3f623f673f6d,0x3f3e3f463f4e3f55,
0xbf6fbf67bf5fbf55,0xbf7fbf7dbf7abf75,0xbf13bf04bee6bec4,0xbf4abf3ebf31bf22,0xbcc93d493dfb3e48,0xbea1be79be2fbdc9,0x3f093f183f273f35,0x3e893eac3ecf3ef1,
0xbeb8bedbbefcbf0e,0xbd97be16be60be95,0xbf51bf5cbf65bf6d,0xbf1dbf2cbf39bf46,0xbf80bf80bf7ebf7b,0xbf73bf78bf7cbf7f,0xbf58bf4ebf42bf35,0xbf77bf71bf6abf62,
0xbf75bf7bbf7fbf80,0xbf46bf55bf62bf6d,0xbef1bf0ebf22bf35,0xbdc9be48be95bec4,0x3e953e483dc90000,0x3f223f0e3ef13ec4,0x3f623f553f463f35,0x3f7f3f7b3f753f6d,
0x3e953e483dc98000,0x3f223f0e3ef13ec4,0x3f623f553f463f35,0x3f7f3f7b3f753f6d,0x3f753f7b3f7f3f80,0x3f463f553f623f6d,0x3ef13f0e3f223f35,0x3dc93e483e953ec4,
0x3f583f673f733f7b,0x3efc3f183f313f46,0x3f6a3f5c3f4a3f35,0x3f7f3f803f7c3f75,0xbf51bf3ebf27bf0e,0xbf7ebf78bf6fbf62,0x3cc93e163e893ec4,0xbee6beacbe60bdc9,
0xbf09bedbbea1be48,0xbf5fbf4ebf39bf22,0x3ecf3f043f1d3f35,0xbd973d493e2f3e95,0xbf13bf2cbf42bf55,0xbdfbbe79beb8bef1,0xbf80bf7dbf77bf6d,0xbf65bf71bf7abf7f,
0xbeacbef1bf18bf35,0x3e793dc9bd49be48,0x3f3e3f223f043ec4,0x3f7d3f753f673f55,0xbedbbe95be160000,0xbf5cbf46bf2cbf0e,0xbf80bf7fbf78bf6d,0xbf4ebf62bf71bf7b,
0x3f713f623f4e3f35,0x3f783f7f3f803f7b,0x3f2c3f463f5c3f6d,0x3e163e953edb3f0e,0xbf67bf75bf7dbf80,0xbf04bf22bf3ebf55,0x3d49bdc9be79bec4,0x3f183ef13eac3e48,
0xbf27bf04beb8be48,0xbf7cbf71bf5fbf46,0x3f1d3f3e3f583f6d,0xbcc93e163ea13ef1,0x3f653f4e3f313f0e,0x3f7a3f803f7e3f75,0xbe89bedbbf13bf35,0x3ecf3e793d97bdc9,
0xbf42bf5cbf6fbf7b,0xbe2fbeacbefcbf22,0xbf4abf2cbf09bec4,0xbf80bf7dbf73bf62,0x3ee63f183f393f55,0xbe60bd493dfb3e95,0x3f773f673f513f35,0x3f6a3f783f7f3f7f,
0x3f553f6d3f7b3f80,0x3e483ec43f0e3f35,0xbf0ebec4be480000,0xbf7bbf6dbf55bf35,0xbf55bf6dbf7bbf80,0xbe48bec4bf0ebf35,0x3f0e3ec43e480000,0x3f7b3f6d3f553f35,
0xbf0ebec4be488000,0xbf7bbf6dbf55bf35,0xbf55bf6dbf7bbf80,0xbe48bec4bf0ebf35,0x3f0e3ec43e488000,0x3f7b3f6d3f553f35,0x3f553f6d3f7b3f80,0x3e483ec43f0e3f35,
0x3d97be16beb8bf0e,0x3f513f2c3efc3e95,0xbf7ebf71bf58bf35,0xbf39bf5cbf73bf7f,0xbee6be79bcc93e48,0xbf7abf67bf4abf22,0x3f773f803f7c3f6d,0x3ecf3f183f423f62,
0x3f7f3f7d3f6f3f55,0x3f133f3e3f5f3f75,0xbdfbbeacbf09bf35,0x3f313f043ea13dc9,0xbf65bf78bf80bf7b,0xbe60bedbbf1dbf46,0xbe89bd493e2f3ec4,0xbf6abf4ebf27bef1,
0xbf80bf75bf5cbf35,0xbf18bf46bf67bf7b,0x3eac3dc9be16bec4,0x3f783f623f3e3f0e,0x3f2c3ef13e790000,0x3f7d3f7f3f713f55,0x3edb3f223f4e3f6d,0xbf04be95bd493e48,
0xbd49be95bf04bf35,0x3f4e3f223edb3e48,0x3f713f7f3f7d3f6d,0x3e793ef13f2c3f55,0x3f3e3f623f783f80,0xbe163dc93eac3f0e,0xbf67bf46bf18bec4,0xbf5cbf75bf80bf7b,
0xbe603d493ea13f0e,0xbf77bf5cbf31bef1,0x3f6f3f4e3f1d3ec4,0x3f423f673f7c3f7f,0xbf51bf71bf7fbf7b,0x3dfbbe16becfbf22,0xbcc93e793efc3f35,0xbf65bf3ebf09be95,
0xbf7abf80bf73bf55,0xbe89bf04bf39bf62,0x3eb83f183f4a3f6d,0xbf27bedbbe2f3dc9,0x3f133eac3d97be48,0x3f7e3f7d3f6a3f46,0xbf80bf78bf5fbf35,0xbee6bf2cbf58bf75,
0xbf22bf55bf75bf80,0x3ef13e48bdc9bec4,0x3f7f3f7b3f623f35,0x3e953f0e3f463f6d,0xbf46bf0ebe950000,0xbf62bf7bbf7fbf6d,0x3dc9be48bef1bf35,0x3f753f553f223ec4,
0x3f463f0e3e958000,0x3f623f7b3f7f3f6d,0xbdc93e483ef13f35,0xbf75bf55bf22bec4,0xbf22bf55bf75bf80,0x3ef13e48bdc9bec4,0x3f7f3f7b3f623f35,0x3e953f0e3f463f6d,
0xbf6abf3ebefcbe48,0xbf27bf5cbf7abf7f,0x3f7c3f7d3f653f35,0x3dfb3edb3f313f62,0x3cc93eac3f1d3f55,0xbf73bf4ebf13be95,0x3f093e79bd97bec4,0x3f773f803f6f3f46,
0xbecfbf2cbf5fbf7b,0x3f423f043e60bdc9,0xbe2f3e163ee63f35,0xbf7ebf67bf39bef1,0xbf80bf71bf4abf0e,0xbea1bf18bf51bf75,0x3f583f783f7f3f6d,0xbe893d493eb83f22,
0xbe793dc93edb3f35,0xbf80bf75bf4ebf0e,0xbe16bef1bf3ebf6d,0x3f713f463f043e48,0xbf5cbf22beac0000,0xbf2cbf62bf7dbf7b,0x3f183e95bd49bec4,0x3f673f7f3f783f55,
0xbf78bf7fbf67bf35,0x3d49be95bf18bf55,0x3f7d3f623f2c3ec4,0x3eac3f223f5c3f7b,0xbf04bf46bf71bf80,0x3f3e3ef13e16be48,0x3f4e3f753f803f6d,0xbedbbdc93e793f0e,
0x3e893f183f583f7b,0xbf6fbf3ebee6bdc9,0xbd97bedbbf39bf6d,0x3f7c3f5c3f1d3e95,0xbdfb3e793f133f55,0xbf80bf71bf42bef1,0x3ea1bd49becfbf35,0x3f7a3f7d3f5f3f22,
0xbf77bf4ebf09be48,0xbeb8bf2cbf65bf7f,0x3f7f3f673f313ec4,0x3e2f3f043f4a3f75,0xbf7ebf78bf51bf0e,0x3cc9beacbf27bf62,0x3f733f803f6a3f35,0xbe603e163efc3f46,
0x3ec43f353f6d3f80,0xbf6dbf35bec40000,0xbec4bf35bf6dbf80,0x3f6d3f353ec40000,0x3ec43f353f6d3f80,0xbf6dbf35bec40000,0xbec4bf35bf6dbf80,0x3f6d3f353ec40000,
0xbf6dbf35bec48000,0xbec4bf35bf6dbf80,0x3f6d3f353ec48000,0x3ec43f353f6d3f80,0xbf6dbf35bec48000,0xbec4bf35bf6dbf80,0x3f6d3f353ec48000,0x3ec43f353f6d3f80,
0x3f4a3f783f7c3f55,0xbf31beac3d973ef1,0xbf65bf80bf6fbf35,0x3f093e16be89bf22,0x3efc3f4e3f7a3f7b,0xbf6abf2cbea13dc9,0xbf27bf67bf80bf6d,0x3f513f043dfbbe95,
0xbf1dbe793e2f3f0e,0xbf39bf71bf7fbf62,0x3ee63d49beb8bf35,0x3f583f7d3f773f46,0xbf5fbf18be603e48,0xbecfbf3ebf73bf7f,0x3f423edb3cc9bec4,0x3f133f5c3f7e3f75,
0x3f5c3f7f3f713f35,0xbf2cbe953e163f0e,0xbf18bf62bf80bf6d,0x3f673f223e79be48,0x3f783f463edb0000,0x3d493ef13f4e3f7b,0xbf7dbf75bf3ebec4,0x3eacbdc9bf04bf55,
0xbf04bdc93eac3f35,0xbf3ebf75bf7dbf55,0x3f4e3ef13d49bec4,0x3edb3f463f783f7b,0x3e793f223f673f80,0xbf80bf62bf18be48,0x3e16be95bf2cbf6d,0x3f713f7f3f5c3f0e,
0x3f313f713f7e3f55,0xbf65bf18be2f3e95,0xbf7abf78bf42bec4,0x3efc3d49becfbf46,0x3f6f3f2c3e89be48,0x3d973f043f583f7f,0xbf13be163ea13f35,0xbf1dbf67bf80bf62,
0xbf39beac3dfb3f0e,0xbee6bf4ebf7cbf75,0x3e60be79bf27bf6d,0x3f5f3f803f6a3f22,0x3eb83f3e3f773f7b,0xbf7fbf5cbf09bdc9,0xbf51bf7dbf73bf35,0x3f4a3edbbcc9bef1,
0xbdc9bf0ebf62bf80,0x3f753f7b3f463ec4,0xbf22be483e953f35,0xbef1bf55bf7fbf6d,0x3f7f3f553ef10000,0xbe953e483f223f6d,0xbf46bf7bbf75bf35,0x3f623f0e3dc9bec4,
0x3f7f3f553ef18000,0xbe953e483f223f6d,0xbf46bf7bbf75bf35,0x3f623f0e3dc9bec4,0x3dc93f0e3f623f80,0xbf75bf7bbf46bec4,0x3f223e48be95bf35,0x3ef13f553f7f3f6d,
0x3e2fbeacbf42bf7b,0x3f4a3f7d3f6f3f22,0x3f393f783f773f35,0xbf73bf2cbe603e95,0x3f583f803f653f0e,0xbf5fbf04bcc93ef1,0xbf6abf18bdfb3ec4,0x3d97bedbbf51bf7f,
0x3f7c3f713f273e48,0xbf1dbe163eb83f46,0xbf31be793e893f35,0xbea1bf3ebf7abf75,0xbf09bd493ee63f55,0xbefcbf5cbf80bf62,0xbecfbf4ebf7ebf6d,0x3f7f3f673f133dc9,
0x3f3e3e95be79bf35,0x3e163f223f713f7b,0xbf67bf7fbf4ebec4,0x3f5c3ef1bd49bf0e,0xbf80bf62bf040000,0x3f183dc9bedbbf55,0x3eac3f463f7d3f6d,0xbf78bf75bf2cbe48,
0x3f2c3f753f783f35,0xbf7dbf46beac3e48,0x3edbbdc9bf18bf6d,0x3f043f623f803f55,0x3d49bef1bf5cbf80,0x3f4e3f7f3f673f0e,0xbf71bf22be163ec4,0x3e79be95bf3ebf7b,
0x3f733f783f313e48,0xbf58bedb3dfb3f22,0xbefc3d493f133f6d,0xbeb8bf4ebf7fbf62,0xbf42bf7dbf6abf0e,0x3f7c3f3e3e89be95,0x3f4a3eacbe60bf35,0xbcc93f043f653f7f,
0xbea13e793f393f7b,0xbf09bf67bf7ebf46,0xbf5fbf80bf51bec4,0x3f6f3f183d97bef1,0x3f273e16becfbf55,0x3e2f3f2c3f773f75,0x3f1d3f713f7a3f35,0xbf80bf5cbee63dc9,
0xbe483ec43f553f80,0xbf0ebf6dbf7bbf35,0x3f7b3f6d3f0e0000,0xbf55bec43e483f35,0x3e48bec4bf55bf80,0x3f0e3f6d3f7b3f35,0xbf7bbf6dbf0e0000,0x3f553ec4be48bf35,
0xbf7bbf6dbf0e8000,0x3f553ec4be48bf35,0xbe483ec43f553f80,0xbf0ebf6dbf7bbf35,0x3f7b3f6d3f0e8000,0xbf55bec43e483f35,0x3e48bec4bf55bf80,0x3f0e3f6d3f7b3f35,
0xbf73bf18bcc93f0e,0x3f09bd49bf1dbf75,0xbefcbf67bf7cbf35,0x3f6f3f783f273dc9,0x3f7f3f5c3ecfbe48,0xbf51beac3e893f46,0x3dfb3f2c3f7a3f6d,0xbf39bf7dbf65bef1,
0xbea1bf4ebf80bf55,0x3f583f803f4a3e95,0x3f5f3edbbe2fbf35,0xbeb83e793f423f7f,0xbd973f043f6a3f7b,0xbf13bf71bf77bf22,0xbf7ebf3ebe603ec4,0x3f313e16bee6bf62,
0xbedbbf62bf7dbf35,0x3f5c3f7f3f3e3e48,0xbf80bf46be793ec4,0x3f4e3e95beacbf55,0x3f713f753f180000,0xbf78bf22bd493f0e,0x3f2c3dc9bf04bf6d,0xbe163ef13f673f7b,
0x3f673ef1be16bf35,0xbf043dc93f2c3f7b,0xbd49bf22bf78bf6d,0x3f183f753f713f0e,0xbeac3e953f4e3f80,0xbe79bf46bf80bf55,0x3f3e3f7f3f5c3ec4,0xbf7dbf62bedb3e48,
0x3f7c3f2c3d97bf0e,0xbf4abe793ecf3f62,0x3f313f7d3f5f3ec4,0xbf73bf71bf093dc9,0xbe603edb3f653f7b,0xbe89bf4ebf80bf46,0xbf6fbf043dfb3f35,0x3f273d49bf13bf75,
0x3e2f3f3e3f7f3f55,0xbf1dbf78bf6abef1,0xbf39be163efc3f6d,0x3ea1beacbf58bf7f,0xbf7abf67bee63e48,0x3f773f18bcc9bf22,0xbeb8bf5cbf7ebf35,0x3f423f803f513e95,
0x3ef1be48bf46bf80,0xbdc93f0e3f753f6d,0xbe95bf55bf7fbf35,0x3f223f7b3f623ec4,0xbf62bf7bbf220000,0x3f7f3f553e95bec4,0xbf75bf0e3dc93f35,0x3f463e48bef1bf6d,
0x3f623f7b3f228000,0xbf7fbf55be953ec4,0x3f753f0ebdc9bf35,0xbf46be483ef13f6d,0x3ef1be48bf46bf80,0xbdc93f0e3f753f6d,0xbe95bf55bf7fbf35,0x3f223f7b3f623ec4,
0x3f393f803f4a3e48,0xbf65bf78bf133dc9,0x3e603f4e3f7f3f35,0xbefcbf71bf6fbef1,0x3f6a3edbbe89bf55,0xbf42be163f093f75,0x3f7c3f5c3ea1bec4,0xbf7ebf2cbcc93f22,
0xbf31bd493f1d3f7b,0x3ee6be79bf51bf7f,0xbf7abf183d973f35,0x3f5f3eacbeb8bf62,0x3ecf3f673f773f0e,0xbf27bf7dbf58be95,0xbe2f3f043f733f6d,0xbdfbbf3ebf80bf46,
0xbf7dbf223d493f35,0x3f713ef1be79bf55,0xbf5cbe953edb3f6d,0x3f3e3dc9bf18bf7b,0xbf4ebf7fbf2c0000,0x3f673f753f04be48,0xbf78bf62beac3ec4,0x3f803f463e16bf0e,
0xbe16bf46bf80bf35,0x3eac3f623f783f0e,0xbf04bf75bf67bec4,0x3f2c3f7f3f4e3e48,0x3f18bdc9bf3ebf80,0xbedb3e953f5c3f7b,0x3e79bef1bf71bf6d,0xbd493f223f7d3f55,
0x3f4a3e16bf13bf7b,0xbf39bd493f273f7f,0x3f653eacbecfbf6d,0xbf58be793efc3f75,0x3f773f04be60bf55,0xbf6fbedb3ea13f62,0x3f7f3f2cbcc9bf35,0xbf7cbf183dfb3f46,
0x3f1d3f7d3f513e48,0xbf31bf80bf42bdc9,0x3ee63f713f6a3ec4,0xbf09bf78bf5fbe95,0x3e893f5c3f7a3f0e,0xbeb8bf67bf73bef1,0x3d973f3e3f803f35,0xbe2fbf4ebf7ebf22,
0xbf8000003f80,0xbf8000003f80,0xbf8000003f80,0xbf8000003f80,0xbf8000003f80,0xbf8000003f80,0xbf8000003f80,0xbf8000003f80,
0x3f808000bf808000,0x3f808000bf808000,0x3f808000bf808000,0x3f808000bf808000,0x3f808000bf808000,0x3f808000bf808000,0x3f808000bf808000,0x3f808000bf808000,
0x3f773e79bf7abe48,0x3f6f3eacbf73be95,0x3f7f3d49bf800000,0x3f7c3e16bf7ebdc9,0x3f4a3f18bf51bf0e,0x3f393f2cbf42bf22,0x3f653edbbf6abec4,0x3f583f04bf5fbef1,
0xbe893f783e60bf7b,0xbeb83f713ea1bf75,0xbd973f803cc9bf80,0xbe2f3f7d3dfbbf7f,0xbf1d3f4e3f13bf55,0xbf313f3e3f27bf46,0xbee63f673ecfbf6d,0xbf093f5c3efcbf62,
0xbf4e3f223f3ebf35,0xbf673ef13f5cbf0e,0xbf783e953f71bec4,0xbf803dc93f7dbe48,0xbe163f7f3d49bf80,0xbeac3f753e79bf7b,0xbf043f623edbbf6d,0xbf2c3f463f18bf55,
0xbf18bf463f2c3f35,0xbedbbf623f043f55,0xbe79bf753eac3f6d,0xbd49bf7f3e163f7b,0xbf7dbdc93f808000,0xbf71be953f783e48,0xbf5cbef13f673ec4,0xbf3ebf223f4e3f0e,
0x3ecfbf71be893f7b,0x3f27bf4ebf093f62,0xbe2fbf783ea13f6d,0x3dfbbf803cc93f7f,0xbf31bf2c3f4a3f0e,0xbee6bf5c3f133f46,0xbf7abe163f7f0000,0xbf5fbedb3f6f3e95,
0x3f6a3eacbf77be48,0x3f423f18bf58bef1,0x3f7cbe79bf733ec4,0x3f7e3d49bf803dc9,0x3f39bf3ebf1d3f55,0x3f65bf04bf513f22,0x3e60bf7dbd973f80,0x3efcbf67beb83f75,
0x3e95bf7bbdc93f80,0x3f22bf55bef13f6d,0x3f62bf0ebf463f35,0x3f7fbe48bf753ec4,0x3f753e48bf7f0000,0x3f463f0ebf62bec4,0x3ef13f55bf22bf35,0x3dc93f7bbe95bf6d,
0x3f753e48bf7f8000,0x3f463f0ebf62bec4,0x3ef13f55bf22bf35,0x3dc93f7bbe95bf6d,0xbe953f7b3dc9bf80,0xbf223f553ef1bf6d,0xbf623f0e3f46bf35,0xbf7f3e483f75bec4,
0x3e603f71bee6bf55,0xbe893f7d3cc9bf7f,0x3f6f3e79bf7e0000,0x3f273f2cbf51bef1,0xbf7cbd493f7fbe48,0xbf4abf043f6a3e95,0xbf313f4e3efcbf6d,0xbf733edb3f58bf22,
0xbf7a3eac3f65bf0e,0xbf77be163f80bdc9,0xbeb83f783dfbbf80,0xbf423f3e3f13bf62,0x3e2fbf803d973f7b,0x3f1dbf5cbecf3f75,0xbf39bf183f5f3ec4,0xbea1bf673f093f46,
0xbeacbf623f183f35,0x3e79bf7f3d493f7b,0x3f3ebf46bf043f6d,0x3f7dbe95bf673f0e,0xbedb3f753e16bf80,0xbf5c3f223f2cbf55,0xbf803dc93f78bec4,0xbf4ebef13f713e48,
0x3f71bef1bf4e3f35,0x3f783dc9bf803e48,0x3f2c3f22bf5cbec4,0x3e163f75bedbbf55,0xbf67be953f7d8000,0xbf04bf463f3e3f0e,0x3d49bf7f3e793f6d,0x3f18bf62beac3f7b,
0x3d973f78becfbf55,0xbf133f673e89bf7f,0x3f7ebd49bf7a3ec4,0x3f313f18bf65be95,0x3ea1bf7d3cc93f7b,0x3f58bf2cbf1d3f62,0xbf5fbeac3f7c0000,0xbeb8bf5c3f273f22,
0xbf7f3e793f6abf0e,0xbf51bedb3f773dc9,0xbdfb3f80be60bf6d,0xbf393f4e3ee6bf75,0x3f733e16bf803e48,0x3f093f3ebf4abef1,0x3efcbf71be2f3f80,0x3f6fbf04bf423f46,
0x3f0ebf6dbe483f80,0x3f7bbec4bf553f35,0x3f553ec4bf7b0000,0x3e483f6dbf0ebf35,0xbf0e3f6d3e48bf80,0xbf7b3ec43f55bf35,0xbf55bec43f7b0000,0xbe48bf6d3f0e3f35,
0x3f553ec4bf7b8000,0x3e483f6dbf0ebf35,0xbf0e3f6d3e48bf80,0xbf7b3ec43f55bf35,0xbf55bec43f7b8000,0xbe48bf6d3f0e3f35,0x3f0ebf6dbe483f80,0x3f7bbec4bf553f35,
0xbf423f4e3ecfbf7b,0xbf7c3d493f77bef1,0x3f4a3edbbf7a0000,0x3cc93f78bee6bf46,0x3f73bf04bf393f55,0x3f583eacbf7e3dc9,0xbefcbf3e3f513ec4,0x3eb8bf7d3d973f75,
0xbf27bf183f6a3e48,0x3e2fbf803e893f62,0xbf1d3f673e60bf80,0xbf803e793f65bf22,0x3ea13f5cbf31bf0e,0xbf093f713dfbbf7f,0x3f5fbf2cbf133f6d,0x3f6f3e16bf7f3e95,
0x3f80be95bf5c3f35,0x3f183f22bf67be48,0xbeac3f7fbe16bf6d,0xbf783ef13f3ebf55,0xbf2c3f623e79bf80,0xbf7d3dc93f71bf0e,0xbedbbf463f4e3ec4,0x3f04bf75bd493f7b,
0x3d493f75bf04bf35,0xbf4e3f463edbbf7b,0xbf71bdc93f7dbec4,0xbe79bf623f2c3f0e,0xbf3ebef13f788000,0x3e16bf7f3eac3f55,0x3f67bf22bf183f6d,0x3f5c3e95bf803e48,
0xbf09bf2c3f653e48,0x3efcbf783cc93f75,0xbecf3f7dbdfbbf6d,0xbf7f3eac3f51bf46,0x3f7cbedbbf423f55,0x3f1d3f18bf6fbdc9,0xbf31bf043f770000,0x3ea1bf803e603f62,
0x3f58bf3ebee63f7b,0x3f5f3e79bf803e95,0xbf6abe163f7ebec4,0xbd97bf713f133f22,0x3e2f3f67bf27bf0e,0xbf4a3f4e3eb8bf7f,0x3f39bf5cbe893f80,0x3f733d49bf7a3ef1,
0x3f46bf55be953f80,0x3f623e48bf7f3ec4,0xbdc93f7bbef1bf35,0xbf753f0e3f22bf6d,0xbf22bf0e3f750000,0x3ef1bf7b3dc93f6d,0x3f7fbe48bf623f35,0x3e953f55bf46bec4,
0x3f223f0ebf758000,0xbef13f7bbdc9bf6d,0xbf7f3e483f62bf35,0xbe95bf553f463ec4,0x3f46bf55be953f80,0x3f623e48bf7f3ec4,0xbdc93f7bbef1bf35,0xbf753f0e3f22bf6d,
0xbf6fbd493f77bf0e,0x3d97bf783f093f22,0x3f133f18bf730000,0xbf1d3f713cc9bf75,0xbf313f673dfbbf7b,0xbf65be163f7cbef1,0x3f7abf04bf273f6d,0x3efc3f2cbf6abdc9,
0x3eb8bf803e893f55,0x3f7fbe79bf583f46,0xbf513f4e3ea1bf80,0xbf4abeac3f80be95,0xbf39bedb3f7ebe48,0x3ee6bf7d3e2f3f62,0x3e603f5cbf42bec4,0xbf5f3f3e3ecfbf7f,
0xbe793f7fbedbbf35,0xbf803e953f4ebf55,0xbe16bf623f3e3ec4,0x3f71bf22bf043f7b,0xbf5c3f463eacbf80,0xbf2cbef13f7dbe48,0x3f18bf753d493f6d,0x3f673dc9bf783f0e,
0xbf783dc93f67bf35,0x3d49bf753f183f0e,0x3f7dbef1bf2c3f6d,0x3eac3f46bf5cbe48,0xbf04bf223f718000,0x3f3ebf62be163f7b,0x3f4e3e95bf803ec4,0xbedb3f7fbe79bf55,
0x3f5f3e16bf7a3f0e,0xbecf3f80bea1bf46,0xbf42beac3f80bec4,0x3f13bf783dfb3f62,0x3f1d3f04bf7c3e48,0xbf393f673d97bf75,0xbee6bf2c3f6f0000,0x3f58bf4ebe893f7f,
0xbefc3f7dbe60bf55,0xbf6abd493f73bf22,0x3f27bf713cc93f6d,0x3f513e79bf7e3ef1,0xbf4a3f5c3e2fbf7b,0xbf31bedb3f7fbe95,0x3f65bf3ebeb83f80,0x3f093f18bf773dc9,
0x3f6dbf35bec43f80,0x3ec43f35bf6d0000,0xbf6d3f353ec4bf80,0xbec4bf353f6d0000,0x3f6dbf35bec43f80,0x3ec43f35bf6d0000,0xbf6d3f353ec4bf80,0xbec4bf353f6d0000,
0x3ec43f35bf6d8000,0xbf6d3f353ec4bf80,0xbec4bf353f6d8000,0x3f6dbf35bec43f80,0x3ec43f35bf6d8000,0xbf6d3f353ec4bf80,0xbec4bf353f6d8000,0x3f6dbf35bec43f80,
0xbdfbbf5c3f513e48,0x3f80bedbbf273f75,0x3ea13f3ebf6a0000,0xbf7a3f183efcbf7f,0x3e89bf7d3f093f0e,0x3f6fbd49bf653f46,0xbd973f71bf31bec4,0xbf7c3e793f4abf62,
0x3f7ebf04bf133f7b,0x3cc93f67bf42be95,0xbf733f2c3ecfbf80,0xbe60bf4e3f5f3dc9,0x3f77be16bf583f55,0xbeb83f80bee6bf22,0xbf7f3eac3f39bf6d,0x3e2fbf783f1d3ef1,
0xbf5cbdc93f71bf35,0x3f2cbf753e163f55,0x3f183ef1bf803ec4,0xbf673f463e79bf7b,0xbf783f223edbbf80,0xbd49bf623f4e3e48,0x3f7dbe95bf3e3f6d,0xbeac3f7fbf04bf0e,
0x3f04bf7f3eac3f35,0x3f3e3e95bf7d3f0e,0xbf4e3f623d49bf6d,0xbedbbf223f78be48,0xbe79bf463f678000,0x3f80bef1bf183f7b,0xbe163f75bf2cbec4,0xbf713dc93f5cbf55,
0xbf803edb3f1dbf7b,0x3ea1bf7d3f133ef1,0x3f58bf5cbd973f6d,0x3e893f3ebf6f3dc9,0xbecf3f80befcbf0e,0xbf42be793f7abf22,0xbe2fbf4e3f650000,0x3f7ebeacbf313f75,
0x3cc9bf673f4a3e48,0x3f73be16bf513f62,0x3f093f04bf7f3ec4,0xbf773f2c3eb8bf7f,0xbf6a3d493f5fbf55,0x3f27bf783e603f46,0x3f7cbf18bee63f80,0xbdfb3f71bf39be95,
0x3f7fbf0ebef13f80,0xbe953f7bbf22bec4,0xbf46be483f75bf35,0x3f62bf55bdc93f6d,0x3dc93f55bf620000,0xbf753e483f46bf6d,0x3f22bf7b3e953f35,0x3ef13f0ebf7f3ec4,
0x3dc93f55bf628000,0xbf753e483f46bf6d,0x3f22bf7b3e953f35,0x3ef13f0ebf7f3ec4,0xbf7f3f0e3ef1bf80,0x3e95bf7b3f223ec4,0x3f463e48bf753f35,0xbf623f553dc9bf6d,
0x3f51bf673d973f55,0x3dfb3f4ebf6a3dc9,0x3cc93f5cbf5f0000,0xbf653d493f58bf62,0x3e603f3ebf733e48,0xbf773e793f39bf75,0xbf6f3e163f4abf6d,0x3f42bf713e2f3f46,
0x3f133edbbf7f3f0e,0xbf7e3f183ecfbf7f,0xbf803f043efcbf80,0x3ee6bf803f093ef1,0xbf7a3f2c3ea1bf7b,0x3e89bf783f313e95,0x3eb8bf7d3f1d3ec4,0x3f273eacbf7c3f22,
0x3f3ebf753e793f35,0x3e163f46bf713e48,0xbf673dc93f4ebf6d,0x3f5cbf623d493f55,0xbf803ef13f04bf80,0x3f18bf7f3edb3f0e,0x3eac3f22bf7d3ec4,0xbf783e953f2cbf7b,
0x3f2c3e95bf783f35,0xbf7d3f223eacbf7b,0x3edbbf7f3f183ec4,0x3f043ef1bf803f0e,0x3d49bf623f5c8000,0x3f4e3dc9bf673f55,0xbf713f463e16bf6d,0x3e79bf753f3e3e48,
0x3f65bf5c3cc93f55,0xbe603f71bf4abdc9,0x3e893f2cbf7c3ec4,0xbf6a3e163f42bf75,0xbf7f3f183eb8bf7b,0x3f13bf803efc3ef1,0x3dfbbf673f580000,0x3f313e79bf733f46,
0x3ee63f04bf803f0e,0xbf7a3eac3f1dbf7f,0xbf773f3e3e2fbf6d,0x3ecfbf7d3f273e95,0xbd97bf4e3f6fbe48,0x3f513d49bf5f3f62,0x3f7ebedbbf093f80,0xbf393f78bea1bf22,
0x3f7bbec4bf0e3f80,0xbf553f6dbe48bf35,0x3e48bf6d3f550000,0x3f0e3ec4bf7b3f35,0xbf7b3ec43f0ebf80,0x3f55bf6d3e483f35,0xbe483f6dbf550000,0xbf0ebec43f7bbf35,
0xbe483f6dbf558000,0xbf0ebec43f7bbf35,0x3f7bbec4bf0e3f80,0xbf553f6dbe48bf35,0x3e48bf6d3f558000,0x3f0e3ec4bf7b3f35,0xbf7b3ec43f0ebf80,0x3f55bf6d3e483f35,
0x3f65be16bf393f7b,0xbf7a3f3e3dfbbf62,0xbe893f71bf510000,0xbecfbf043f7fbf22,0xbf27be793f6fbf55,0x3f7cbedbbefc3f7f,0x3f1dbf803f093ec4,0x3cc93f4ebf733e95,
0xbee63f7dbf31be48,0xbe60bf2c3f7ebef1,0xbf773eac3f13bf80,0x3f6abf5c3d973f46,0x3f42bf783eb83f0e,0xbe2f3f67bf5f3dc9,0x3f4a3d49bf583f6d,0xbf803f183ea1bf75,
0x3edb3ef1bf7d3f35,0xbf5c3dc93f3ebf7b,0x3f80bf22be793f6d,0xbf4e3f75beacbf0e,0xbf713e953f18bf80,0x3f78bf46bd493f55,0xbf2c3f7fbf04bec4,0x3e16bf623f67be48,
0xbf673f62be16bf35,0x3f04bf7f3f2c3e48,0x3d493f46bf783ec4,0xbf18be953f71bf55,0x3eacbf753f4e8000,0x3e793f22bf803f0e,0xbf3ebdc93f5cbf6d,0x3f7dbef1bedb3f7b,
0xbf133f80bf27be48,0x3dfbbf5c3f6fbe95,0xbf803f183e89bf6d,0x3f65bf673e603f22,0xbf09beac3f73bf55,0x3f5fbe16bf313f7f,0x3ecfbf783f4a0000,0x3d973f3ebf7c3ef1,
0xbf513d493f42bf7b,0x3f7ebf04beb83f75,0x3cc9bf4e3f77bec4,0x3ee63edbbf7a3f46,0x3f58bf713ea13f0e,0xbefc3f7dbf39bdc9,0x3f6abe79bf1d3f80,0xbf7f3f2c3e2fbf62,
0x3f62be48bf223f80,0xbf7f3f0e3e95bf6d,0x3f75bf553dc93f35,0xbf463f7bbef1bec4,0x3ef1bf7b3f460000,0xbdc93f55bf753ec4,0xbe95bf0e3f7fbf35,0x3f223e48bf623f6d,
0xbef13f7bbf468000,0x3dc9bf553f75bec4,0x3e953f0ebf7f3f35,0xbf22be483f62bf6d,0x3f62be48bf223f80,0xbf7f3f0e3e95bf6d,0x3f75bf553dc93f35,0xbf463f7bbef1bec4,
0x3cc93f3ebf7e3f0e,0xbea1bf043f7cbf46,0xbf093f7dbf420000,0x3e89bf673f6abe95,0x3f6fbeacbefc3f7b,0xbf7f3f183e60bf62,0x3f133e79bf653f6d,0xbf4a3d493f39bf7f,
0xbf803f2c3dfbbf55,0x3f73bf5c3e2f3f22,0xbf583e163f27bf80,0x3f77bedbbecf3f75,0xbeb83f71bf5f3e48,0x3d97bf4e3f7abef1,0xbf513f78bee6bec4,0x3f1dbf803f313dc9,
0xbf7d3f46bd49bf35,0x3f71bf623e793f0e,0xbf5c3f75bedbbec4,0x3f3ebf7f3f183e48,0xbf4e3dc93f2cbf80,0x3f67be95bf043f7b,0xbf783ef13eacbf6d,0x3f80bf22be163f55,
0xbe16bf223f80bf35,0x3eac3ef1bf783f55,0xbf04be953f67bf6d,0x3f2c3dc9bf4e3f7b,0x3f18bf7f3f3e8000,0xbedb3f75bf5c3e48,0x3e79bf623f71bec4,0xbd493f46bf7d3f0e,
0x3dfbbf4e3f7cbf0e,0xbcc93f3ebf7f3f22,0x3ea1bf673f6fbec4,0xbe603f5cbf773ef1,0x3efcbf783f58be48,0xbecf3f71bf653e95,0x3f27bf803f390000,0xbf133f7dbf4a3dc9,
0x3f7ebf18be2f3f55,0xbf803f2c3d97bf46,0x3f73bedbbeb83f6d,0xbf7a3f043e89bf62,0x3f5fbe79bf093f7b,0xbf6a3eac3ee6bf75,0x3f42bd49bf313f80,0xbf513e163f1dbf7f,
0xbf8000003f80,0xbf8000003f80,0xbf8000003f80,0xbf8000003f80,0xbf8000003f80,0xbf8000003f80,0xbf8000003f80,0xbf8000003f80,
0x3f808000bf808000,0x3f808000bf808000,0x3f808000bf808000,0x3f808000bf808000,0x3f808000bf808000,0x3f808000bf808000,0x3f808000bf808000,0x3f808000bf808000,
0x3efc3f5cbf09bf55,0x3ecf3f67bee6bf62,0x3f273f3ebf31bf35,0x3f133f4ebf1dbf46,0x3dfb3f7dbe2fbf7b,0x3cc93f80bd97bf7f,0x3ea13f71beb8bf6d,0x3e603f78be89bf75,
0xbf5f3f043f58bf0e,0xbf6a3edb3f65bef1,0xbf423f2c3f39bf35,0xbf513f183f4abf22,0xbf7e3e163f7cbe48,0xbf803d493f7fbdc9,0xbf733eac3f6fbec4,0xbf7a3e793f77be95,
0xbf18bf463f2c3f35,0xbedbbf623f043f55,0xbe79bf753eac3f6d,0xbd49bf7f3e163f7b,0xbf7dbdc93f800000,0xbf71be953f783e48,0xbf5cbef13f673ec4,0xbf3ebf223f4e3f0e,
0x3f4ebf22bf3e3f35,0x3f67bef1bf5c3f0e,0x3f78be95bf713ec4,0x3f80bdc9bf7d3e48,0x3e16bf7fbd493f80,0x3eacbf75be793f7b,0x3f04bf62bedb3f6d,0x3f2cbf46bf183f55,
0x3eb83f67befcbf55,0x3d973f7dbe60bf75,0x3f513f04bf65bec4,0x3f1d3f3ebf39bf22,0x3f80bd49bf7e3e48,0x3f733e79bf7cbdc9,0x3f58bf18bf423f35,0x3f77beacbf6a3ef1,
0xbf6f3edb3f5fbf0e,0xbf7f3e163f7abe95,0xbf133f5c3ee6bf6d,0xbf4a3f2c3f31bf46,0xbcc93f80bdfbbf7b,0xbea13f783e2fbf7f,0x3f093f4ebf27bf35,0x3e893f71becfbf62,
0xbe953f7b3dc9bf80,0xbf223f553ef1bf6d,0xbf623f0e3f46bf35,0xbf7f3e483f75bec4,0xbf75be483f7f0000,0xbf46bf0e3f623ec4,0xbef1bf553f223f35,0xbdc9bf7b3e953f6d,
0xbf75be483f7f8000,0xbf46bf0e3f623ec4,0xbef1bf553f223f35,0xbdc9bf7b3e953f6d,0x3e95bf7bbdc93f80,0x3f22bf55bef13f6d,0x3f62bf0ebf463f35,0x3f7fbe48bf753ec4,
0x3f09bf67bea13f7b,0x3f5fbf18bf393f46,0xbecfbf5c3f1d3f35,0x3d97bf803e2f3f75,0x3f133f3ebf42bf0e,0x3dfb3f78beb8bf62,0x3f80be16bf773ec4,0x3f653eacbf7abdc9,
0x3f583edbbf73be48,0x3efc3f4ebf31bf22,0x3f6abf04bf4a3f35,0x3f7fbd49bf7c3e95,0xbf513f2c3f27bf55,0xbf7e3e793f6fbef1,0x3cc93f7dbe89bf6d,0xbee63f713e60bf7f,
0xbf713ef13f4ebf35,0xbf78bdc93f80be48,0xbf2cbf223f5c3ec4,0xbe16bf753edb3f55,0x3f673e95bf7d0000,0x3f043f46bf3ebf0e,0xbd493f7fbe79bf6d,0xbf183f623eacbf7b,
0xbeacbf623f183f35,0x3e79bf7f3d493f7b,0x3f3ebf46bf043f6d,0x3f7dbe95bf673f0e,0xbedb3f753e16bf80,0xbf5c3f223f2cbf55,0xbf803dc93f78bec4,0xbf4ebef13f713e48,
0x3f423f04bf6fbe48,0x3e2f3f71befcbf46,0x3f4abf3ebf093f6d,0x3f80be16bf733ef1,0xbee6bf4e3f393f0e,0x3e60bf803dfb3f75,0xbf773edb3f51bf35,0xbf6abe793f7fbdc9,
0xbf273f5c3eb8bf7b,0xbf7c3eac3f5fbf22,0x3f1d3f2cbf58bec4,0xbcc93f7dbea1bf62,0x3f65bf18bf313f55,0x3f7a3d49bf7e3e95,0xbe89bf673f133f35,0x3ecfbf78bd973f7f,
0x3f0ebf6dbe483f80,0x3f7bbec4bf553f35,0x3f553ec4bf7b0000,0x3e483f6dbf0ebf35,0xbf0e3f6d3e48bf80,0xbf7b3ec43f55bf35,0xbf55bec43f7b0000,0xbe48bf6d3f0e3f35,
0x3f553ec4bf7b8000,0x3e483f6dbf0ebf35,0xbf0e3f6d3e48bf80,0xbf7b3ec43f55bf35,0xbf55bec43f7b8000,0xbe48bf6d3f0e3f35,0x3f0ebf6dbe483f80,0x3f7bbec4bf553f35,
0xbf7f3e163f6fbf0e,0xbf13bf2c3f5f3e95,0x3dfb3f71bf09bf35,0xbf313f5c3ea1bf7f,0x3f653e79bf803e48,0x3e603f67bf1dbf22,0x3e89bf803e2f3f6d,0x3f6abf18bf273f62,
0x3d97bf7d3eb83f55,0x3f51bf3ebefc3f75,0xbf7e3eac3f58bf35,0xbf39bf043f733dc9,0xbee63f783cc9bf7b,0xbf7a3edb3f4abf46,0x3f773d49bf7c3ec4,0x3ecf3f4ebf42bef1,
0x3d493f75bf04bf35,0xbf4e3f463edbbf7b,0xbf71bdc93f7dbec4,0xbe79bf623f2c3f0e,0xbf3ebef13f780000,0x3e16bf7f3eac3f55,0x3f67bf22bf183f6d,0x3f5c3e95bf803e48,
0xbf803e953f5cbf35,0xbf18bf223f673e48,0x3eacbf7f3e163f6d,0x3f78bef1bf3e3f55,0x3f2cbf62be793f80,0x3f7dbdc9bf713f0e,0x3edb3f46bf4ebec4,0xbf043f753d49bf7b,
0x3f7abd49bf733f0e,0x3e893f5cbf39bef1,0xbeb8bf4e3f4a3ec4,0x3f27bf67be2f3f7f,0xbf133f713d97bf7b,0xbf7e3e163f6abf22,0x3f80be79bf5f3f35,0x3ee63f3ebf58be95,
0xbe603f80bea1bf55,0xbf773f043f31bf62,0x3f6fbf18bf1d3f6d,0x3f423edbbf7c3dc9,0xbf51beac3f7fbe48,0x3dfbbf7d3ecf3f46,0xbcc93f78befcbf35,0xbf653f2c3f09bf75,
0xbf463f553e95bf80,0xbf62be483f7fbec4,0x3dc9bf7b3ef13f35,0x3f75bf0ebf223f6d,0x3f223f0ebf750000,0xbef13f7bbdc9bf6d,0xbf7f3e483f62bf35,0xbe95bf553f463ec4,
0xbf22bf0e3f758000,0x3ef1bf7b3dc93f6d,0x3f7fbe48bf623f35,0x3e953f55bf46bec4,0xbf463f553e95bf80,0xbf62be483f7fbec4,0x3dc9bf7b3ef13f35,0x3f75bf0ebf223f6d,
0x3ecf3f3ebf5fbe48,0xbf423f5c3e60bf7f,0x3e2fbf7d3ee63f35,0x3f7ebedbbf393f62,0x3f80beacbf4a3f55,0x3ea13f4ebf51be95,0xbf58be793f7fbec4,0x3e89bf803eb83f46,
0xbf6a3f2c3efcbf7b,0xbf27bf043f7abdc9,0x3f7cbe16bf653f35,0x3dfb3f67bf31bef1,0x3cc93f71bf1dbf0e,0xbf733f183f13bf75,0x3f09bf783d973f6d,0x3f77bd49bf6f3f22,
0x3f78bdc9bf673f35,0xbd493f75bf18bf0e,0xbf7d3ef13f2cbf6d,0xbeacbf463f5c3e48,0x3f043f22bf710000,0xbf3e3f623e16bf7b,0xbf4ebe953f80bec4,0x3edbbf7f3e793f55,
0xbe793f7fbedbbf35,0xbf803e953f4ebf55,0xbe16bf623f3e3ec4,0x3f71bf22bf043f7b,0xbf5c3f463eacbf80,0xbf2cbef13f7dbe48,0x3f18bf753d493f6d,0x3f673dc9bf783f0e,
0x3f77bf18bf093f7b,0x3eb83f3ebf65bdc9,0xbf7f3edb3f31bf6d,0xbe2fbf5c3f4a3e95,0x3f7ebe79bf513f55,0xbcc93f71bf27bef1,0xbf733d493f6abf35,0x3e60bf7d3efc3f22,
0x3e893f4ebf58be48,0xbf6f3f2c3ee6bf7f,0xbd97bf673f393ec4,0x3f7cbf04bf1d3f75,0xbdfb3f78bf13bf0e,0xbf803eac3f42bf62,0x3ea1bf803ecf3f35,0x3f7abe16bf5f3f46,
0x3f6dbf35bec43f80,0x3ec43f35bf6d0000,0xbf6d3f353ec4bf80,0xbec4bf353f6d0000,0x3f6dbf35bec43f80,0x3ec43f35bf6d0000,0xbf6d3f353ec4bf80,0xbec4bf353f6d0000,
0x3ec43f35bf6d8000,0xbf6d3f353ec4bf80,0xbec4bf353f6d8000,0x3f6dbf35bec43f80,0x3ec43f35bf6d8000,0xbf6d3f353ec4bf80,0xbec4bf353f6d8000,0x3f6dbf35bec43f80,
0x3f1dbf783e2f3f55,0x3f393eacbf7f3ef1,0xbee63f80beb8bf35,0xbf58be163f77bf22,0x3f5fbf4ebe603f7b,0x3ecf3f2cbf733dc9,0xbf423f673cc9bf6d,0xbf13bf043f7ebe95,
0x3f4a3e79bf7c3f0e,0xbf313f71bd97bf62,0xbf65bd493f6fbf35,0x3f09bf7d3e893f46,0x3efc3f18bf7a3e48,0xbf6a3f3e3ea1bf7f,0xbf27bedb3f80bec4,0x3f51bf5cbdfb3f75,
0x3f04bf7f3eac3f35,0x3f3e3e95bf7d3f0e,0xbf4e3f623d49bf6d,0xbedbbf223f78be48,0xbe79bf463f670000,0x3f80bef1bf183f7b,0xbe163f75bf2cbec4,0xbf713dc93f5cbf55,
0x3f5c3dc9bf713f35,0xbf2c3f75be16bf55,0xbf18bef13f80bec4,0x3f67bf46be793f7b,0x3f78bf22bedb3f80,0x3d493f62bf4ebe48,0xbf7d3e953f3ebf6d,0x3eacbf7f3f043f0e,
0x3f39bf713dfb3f55,0x3ee63f18bf7c3e95,0xbe603f78bf27bec4,0xbf5fbd493f6abf46,0xbeb8bf2c3f77be48,0x3f7fbf04bf093f7f,0x3f513e16bf733f35,0xbf4a3f67bcc9bf62,
0x3f313eacbf7e3f0e,0xbf653f4e3e2fbf75,0xbf7a3e793f42bf6d,0x3efcbf803ecf3f22,0x3f6fbf3ebe893f7b,0x3d973f5cbf58bdc9,0xbf133f7dbea1bf35,0xbf1dbedb3f80bef1,
0xbf7f3f0e3ef1bf80,0x3e95bf7b3f223ec4,0x3f463e48bf753f35,0xbf623f553dc9bf6d,0xbdc9bf553f620000,0x3f75be48bf463f6d,0xbf223f7bbe95bf35,0xbef1bf0e3f7fbec4,
0xbdc9bf553f628000,0x3f75be48bf463f6d,0xbf223f7bbe95bf35,0xbef1bf0e3f7fbec4,0x3f7fbf0ebef13f80,0xbe953f7bbf22bec4,0xbf46be483f75bf35,0x3f62bf55bdc93f6d,
0xbf7c3eac3f27bf7b,0x3f1dbf7d3eb83f22,0x3f31bf783e893f35,0x3ea13f2cbf7a3e95,0x3f09bf803ee63f0e,0x3efc3f04bf803ef1,0x3ecf3f18bf7e3ec4,0xbf7f3edb3f13bf7f,
0x3e2fbf713f423e48,0x3f4a3e16bf6f3f46,0x3f393e79bf773f35,0xbf733f3e3e60bf75,0x3f583d49bf653f55,0xbf5f3f5c3cc9bf62,0xbf6a3f4e3dfbbf6d,0x3d97bf673f513dc9,
0xbf2cbe953f78bf35,0x3f7dbf22beac3f7b,0xbedb3f7fbf18bec4,0xbf04bef13f80bf0e,0xbd493f62bf5c0000,0xbf4ebdc93f67bf55,0x3f71bf46be163f6d,0xbe793f75bf3ebe48,
0x3f3ebf753e793f35,0x3e163f46bf713e48,0xbf673dc93f4ebf6d,0x3f5cbf623d493f55,0xbf803ef13f04bf80,0x3f18bf7f3edb3f0e,0x3eac3f22bf7d3ec4,0xbf783e953f2cbf7b,
0x3ea1bf783f393e48,0x3f093edbbf7e3f22,0x3f5fbd49bf513f6d,0xbf6f3f4e3d97bf62,0xbf273f7dbecfbf0e,0xbe2fbf3e3f77be95,0xbf1dbeac3f7abf35,0x3f80bf04bee63f7f,
0x3f73be79bf313f7b,0xbf583f67bdfbbf46,0xbefc3f80bf13bec4,0xbeb8bf183f7fbef1,0xbf42be163f6abf55,0x3f7cbf2cbe893f75,0x3f4abf713e603f35,0xbcc93f5cbf653dc9,
0x3f7bbec4bf0e3f80,0xbf553f6dbe48bf35,0x3e48bf6d3f550000,0x3f0e3ec4bf7b3f35,0xbf7b3ec43f0ebf80,0x3f55bf6d3e483f35,0xbe483f6dbf550000,0xbf0ebec43f7bbf35,
0xbe483f6dbf558000,0xbf0ebec43f7bbf35,0x3f7bbec4bf0e3f80,0xbf553f6dbe48bf35,0x3e48bf6d3f558000,0x3f0e3ec4bf7b3f35,0xbf7b3ec43f0ebf80,0x3f55bf6d3e483f35,
0x3ea13f18bf803f0e,0xbf583d493f4abf75,0xbf5f3f67be2fbf35,0x3eb8bf783f423dc9,0x3d97bf5c3f6abe48,0x3f133eacbf773f46,0x3f7ebf2cbe603f6d,0xbf313f7dbee6bef1,
0xbf733f4e3cc9bf55,0x3f09bf803f1d3e95,0xbefcbedb3f7cbf35,0x3f6fbe79bf273f7f,0x3f7fbf04becf3f7b,0xbf513f71be89bf22,0x3dfb3f3ebf7a3ec4,0xbf39be163f65bf62,
0xbf673f62be16bf35,0x3f04bf7f3f2c3e48,0x3d493f46bf783ec4,0xbf18be953f71bf55,0x3eacbf753f4e0000,0x3e793f22bf803f0e,0xbf3ebdc93f5cbf6d,0x3f7dbef1bedb3f7b,
0xbedbbef13f7dbf35,0x3f5cbdc9bf3e3f7b,0xbf803f223e79bf6d,0x3f4ebf753eac3f0e,0x3f71be95bf183f80,0xbf783f463d49bf55,0x3f2cbf7f3f043ec4,0xbe163f62bf673e48,
0xbe2fbf2c3f7fbf0e,0x3f1d3e79bf6a3f62,0x3f39bf7d3efc3ec4,0xbea13f71bf583dc9,0x3f7abedbbee63f7b,0xbf773f4ebcc9bf46,0x3eb83f04bf7e3f35,0xbf42bd493f51bf75,
0x3f7cbf3ebd973f55,0xbf4a3f78becfbef1,0x3f313e16bf5f3f6d,0xbf733eac3f09bf7f,0xbe603f67bf653e48,0xbe89bf183f80bf22,0xbf6f3f5cbdfbbf35,0x3f27bf803f133e95,
0xbf623e483f22bf80,0x3f7fbf0ebe953f6d,0xbf753f55bdc9bf35,0x3f46bf7b3ef13ec4,0xbef13f7bbf460000,0x3dc9bf553f75bec4,0x3e953f0ebf7f3f35,0xbf22be483f62bf6d,
0x3ef1bf7b3f468000,0xbdc93f55bf753ec4,0xbe95bf0e3f7fbf35,0x3f223e48bf623f6d,0xbf623e483f22bf80,0x3f7fbf0ebe953f6d,0xbf753f55bdc9bf35,0x3f46bf7b3ef13ec4,
0x3f31bf803f1d3e48,0xbee63f78bf513dc9,0x3f7abf4e3d973f35,0xbf5f3f71beb8bef1,0xbecfbedb3f77bf55,0x3f273e16bf583f75,0x3e2fbf5c3f73bec4,0x3dfb3f2cbf803f22,
0x3f393d49bf4a3f7b,0xbf653e793f13bf7f,0x3e603f18bf7f3f35,0xbefcbeac3f6fbf62,0x3f6abf673e893f0e,0xbf423f7dbf09be95,0x3f7cbf04bea13f6d,0xbf7e3f3e3cc9bf46,
0x3e163f22bf803f35,0xbeacbef13f78bf55,0x3f043e95bf673f6d,0xbf2cbdc93f4ebf7b,0xbf183f7fbf3e0000,0x3edbbf753f5cbe48,0xbe793f62bf713ec4,0x3d49bf463f7dbf0e,
0xbf7d3f46bd49bf35,0x3f71bf623e793f0e,0xbf5c3f75bedbbec4,0x3f3ebf7f3f183e48,0xbf4e3dc93f2cbf80,0x3f67be95bf043f7b,0xbf783ef13eacbf6d,0x3f80bf22be163f55,
0xbf1dbe163f51bf7b,0x3f313d49bf423f7f,0xbee6beac3f6abf6d,0x3f093e79bf5f3f75,0xbe89bf043f7abf55,0x3eb83edbbf733f62,0xbd97bf2c3f80bf35,0x3e2f3f18bf7e3f46,
0x3f4abf7d3f133e48,0xbf393f80bf27bdc9,0x3f65bf713ecf3ec4,0xbf583f78befcbe95,0x3f77bf5c3e603f0e,0xbf6f3f67bea1bef1,0x3f7fbf3e3cc93f35,0xbf7c3f4ebdfbbf22,
0xbf3500003f353f80,0x3f350000bf35bf80,0xbf3500003f353f80,0x3f350000bf35bf80,0xbf3500003f353f80,0x3f350000bf35bf80,0xbf3500003f353f80,0x3f350000bf35bf80,
0xbf35bf80bf358000,0x3f353f803f358000,0xbf35bf80bf358000,0x3f353f803f358000,0xbf35bf80bf358000,0x3f353f803f358000,0xbf35bf80bf358000,0x3f353f803f358000,
0x3e89be793e60be48,0x3eb8beac3ea1be95,0x3d97bd493cc90000,0x3e2fbe163dfbbdc9,0x3f1dbf183f13bf0e,0x3f31bf2c3f27bf22,0x3ee6bedb3ecfbec4,0x3f09bf043efcbef1,
0x3f77bf783f7abf7b,0x3f6fbf713f73bf75,0x3f7fbf803f80bf80,0x3f7cbf7d3f7ebf7f,0x3f4abf4e3f51bf55,0x3f39bf3e3f42bf46,0x3f65bf673f6abf6d,0x3f58bf5c3f5fbf62,
0x3f18bf223f2cbf35,0x3edbbef13f04bf0e,0x3e79be953eacbec4,0x3d49bdc93e16be48,0x3f7dbf7f3f80bf80,0x3f71bf753f78bf7b,0x3f5cbf623f67bf6d,0x3f3ebf463f4ebf55,
0xbf4e3f46bf3e3f35,0xbf673f62bf5c3f55,0xbf783f75bf713f6d,0xbf803f7fbf7d3f7b,0xbe163dc9bd498000,0xbeac3e95be793e48,0xbf043ef1bedb3ec4,0xbf2c3f22bf183f0e,
0xbf6a3f71bf773f7b,0xbf423f4ebf583f62,0xbf7c3f78bf733f6d,0xbf7e3f80bf803f7f,0xbf393f2cbf1d3f0e,0xbf653f5cbf513f46,0xbe603e16bd970000,0xbefc3edbbeb83e95,
0x3ecfbeac3e89be48,0x3f27bf183f09bef1,0xbe2f3e79bea13ec4,0x3dfbbd49bcc93dc9,0xbf313f3ebf4a3f55,0xbee63f04bf133f22,0xbf7a3f7dbf7f3f80,0xbf5f3f67bf6f3f75,
0xbf753f7bbf7f3f80,0xbf463f55bf623f6d,0xbef13f0ebf223f35,0xbdc93e48be953ec4,0x3e95be483dc90000,0x3f22bf0e3ef1bec4,0x3f62bf553f46bf35,0x3f7fbf7b3f75bf6d,
0x3e95be483dc98000,0x3f22bf0e3ef1bec4,0x3f62bf553f46bf35,0x3f7fbf7b3f75bf6d,0x3f75bf7b3f7fbf80,0x3f46bf553f62bf6d,0x3ef1bf0e3f22bf35,0x3dc9be483e95bec4,
0x3f7abf713f65bf55,0x3f77bf7d3f80bf7f,0x3eb8be793dfb0000,0x3f42bf2c3f13bef1,0xbe2f3d493d97be48,0xbf1d3f04becf3e95,0x3f39bf4e3f5fbf6d,0x3ea1bedb3f09bf22,
0x3e60beac3ee6bf0e,0xbe893e16bcc9bdc9,0x3f6fbf783f7ebf80,0x3f27bf3e3f51bf62,0xbf7c3f80bf7f3f7b,0xbf4a3f5cbf6a3f75,0xbf313f18befc3ec4,0xbf733f67bf583f46,
0xbf713f62bf4e3f35,0xbf783f7fbf803f7b,0xbf2c3f46bf5c3f6d,0xbe163e95bedb3f0e,0x3f67bf753f7dbf80,0x3f04bf223f3ebf55,0xbd49bdc93e79bec4,0xbf183ef1beac3e48,
0xbeac3ef1bf183f35,0x3e79bdc9bd493e48,0x3f3ebf223f04bec4,0x3f7dbf753f67bf55,0xbedb3e95be168000,0xbf5c3f46bf2c3f0e,0xbf803f7fbf783f6d,0xbf4e3f62bf713f7b,
0x3f7fbf783f6abf55,0x3f51bf673f77bf7f,0x3dfb3d49be603ec4,0x3f39bf183ee6be95,0xbf733f7dbf803f7b,0xbf093f2cbf4a3f62,0xbefc3eacbe2f0000,0xbf6f3f5cbf423f22,
0x3d97be793ecfbf0e,0xbf133edbbe893dc9,0x3f7ebf803f7abf6d,0x3f31bf4e3f65bf75,0x3ea1be16bcc93e48,0x3f58bf3e3f1dbef1,0xbf5f3f71bf7c3f80,0xbeb83f04bf273f46,
0xbf553f6dbf7b3f80,0xbe483ec4bf0e3f35,0x3f0ebec43e480000,0x3f7bbf6d3f55bf35,0x3f55bf6d3f7bbf80,0x3e48bec43f0ebf35,0xbf0e3ec4be480000,0xbf7b3f6dbf553f35,
0x3f0ebec43e488000,0x3f7bbf6d3f55bf35,0x3f55bf6d3f7bbf80,0x3e48bec43f0ebf35,0xbf0e3ec4be488000,0xbf7b3f6dbf553f35,0xbf553f6dbf7b3f80,0xbe483ec4bf0e3f35,
0x3f27bf4e3f6abf7b,0xbe2fbd493e89bef1,0x3f1dbedb3e600000,0x3f80bf783f65bf46,0xbea13f04bf313f55,0x3f09beac3dfb3dc9,0xbf5f3f3ebf133ec4,0xbf6f3f7dbf7f3f75,
0xbf423f18becf3e48,0xbf7c3f80bf773f62,0x3f4abf673f7abf80,0x3cc9be793ee6bf22,0x3f73bf5c3f39bf0e,0x3f58bf713f7ebf7f,0xbefc3f2cbf513f6d,0x3eb8be16bd973e95,
0xbd493e95bf043f35,0x3f4ebf223edbbe48,0x3f71bf7f3f7dbf6d,0x3e79bef13f2cbf55,0x3f3ebf623f78bf80,0xbe16bdc93eacbf0e,0xbf673f46bf183ec4,0xbf5c3f75bf803f7b,
0x3f80bf753f5cbf35,0x3f18bf463f67bf7b,0xbeac3dc93e16bec4,0xbf783f62bf3e3f0e,0xbf2c3ef1be798000,0xbf7d3f7fbf713f55,0xbedb3f22bf4e3f6d,0x3f04be953d493e48,
0xbf583f2cbee63e48,0xbf5f3f78bf803f75,0x3f6abf7d3f7ebf6d,0x3d97beac3f13bf46,0xbe2f3edbbf273f55,0x3f4abf183eb8bdc9,0xbf393f04be890000,0xbf733f80bf7a3f62,
0xbf093f3ebf653f7b,0x3efcbe79bcc93e95,0xbecf3e163dfbbec4,0xbf7f3f71bf513f22,0x3f7cbf673f42bf0e,0x3f1dbf4e3f6fbf7f,0xbf313f5cbf773f80,0x3ea1bd49be603ef1,
0xbf223f55bf753f80,0x3ef1be48bdc93ec4,0x3f7fbf7b3f62bf35,0x3e95bf0e3f46bf6d,0xbf463f0ebe950000,0xbf623f7bbf7f3f6d,0x3dc93e48bef13f35,0x3f75bf553f22bec4,
0x3f46bf0e3e958000,0x3f62bf7b3f7fbf6d,0xbdc9be483ef1bf35,0xbf753f55bf223ec4,0xbf223f55bf753f80,0x3ef1be48bdc93ec4,0x3f7fbf7b3f62bf35,0x3e95bf0e3f46bf6d,
0xbeb83d493e89bf0e,0xbf7f3f78bf583f22,0x3f51bf183ea10000,0x3f4abf713f80bf75,0x3f39bf673f7ebf7b,0xbee63e163e2fbef1,0xbe603f04bf423f6d,0x3f5fbf2c3ecfbdc9,
0xbf6f3f80bf773f55,0x3d973e79bf093f46,0x3f13bf4e3f73bf80,0xbf1d3eacbcc9be95,0xbf313edbbdfbbe48,0xbf653f7dbf7c3f62,0x3f7abf5c3f27bec4,0x3efcbf3e3f6abf7f,
0x3f78bf7f3f67bf35,0xbd49be953f18bf55,0xbf7d3f62bf2c3ec4,0xbeac3f22bf5c3f7b,0x3f04bf463f71bf80,0xbf3e3ef1be16be48,0xbf4e3f75bf803f6d,0x3edbbdc9be793f0e,
0xbe79bdc93edbbf35,0xbf803f75bf4e3f0e,0xbe163ef1bf3e3f6d,0x3f71bf463f04be48,0xbf5c3f22beac8000,0xbf2c3f62bf7d3f7b,0x3f18be95bd493ec4,0x3f67bf7f3f78bf55,
0x3efcbe16be603f0e,0x3f6abf803f73bf46,0xbf273eac3cc9bec4,0xbf513f78bf7e3f62,0x3f4abf043e2f3e48,0x3f31bf673f7fbf75,0xbf653f2cbeb80000,0xbf093f4ebf773f7f,
0x3f5fbf7d3f7abf55,0xbecf3d493ea1bf22,0xbf423f71bf803f6d,0x3f13be79bdfb3ef1,0x3f1dbf5c3f7cbf7b,0xbf393edbbd97be95,0xbee63f3ebf6f3f80,0x3f58bf183e893dc9,
0xbec43f35bf6d3f80,0x3f6dbf353ec40000,0x3ec4bf353f6dbf80,0xbf6d3f35bec40000,0xbec43f35bf6d3f80,0x3f6dbf353ec40000,0x3ec4bf353f6dbf80,0xbf6d3f35bec40000,
0x3f6dbf353ec48000,0x3ec4bf353f6dbf80,0xbf6d3f35bec48000,0xbec43f35bf6d3f80,0x3f6dbf353ec48000,0x3ec4bf353f6dbf80,0xbf6d3f35bec48000,0xbec43f35bf6d3f80,
0xbf7e3f5cbf133e48,0xbcc93edbbf423f75,0x3f73bf3e3ecf0000,0x3e60bf183f5fbf7f,0xbf773f7dbf583f0e,0x3eb83d49bee63f46,0x3f7fbf713f39bec4,0xbe2fbe793f1dbf62,
0xbdfb3f04bf513f7b,0x3f80bf673f27be95,0x3ea1bf2c3f6abf80,0xbf7a3f4ebefc3dc9,0x3e893e16bf093f55,0x3f6fbf803f65bf22,0xbd97beac3f31bf6d,0xbf7c3f78bf4a3ef1,
0xbf043dc93eacbf35,0xbf3e3f75bf7d3f55,0x3f4ebef13d493ec4,0x3edbbf463f78bf7b,0x3e79bf223f67bf80,0xbf803f62bf183e48,0x3e163e95bf2c3f6d,0x3f71bf7f3f5cbf0e,
0xbf5c3f7fbf713f35,0x3f2cbe95be163f0e,0x3f18bf623f80bf6d,0xbf673f22be79be48,0xbf783f46bedb8000,0xbd493ef1bf4e3f7b,0x3f7dbf753f3ebec4,0xbeacbdc93f04bf55,
0xbcc9bedb3f4abf7b,0xbf733f7dbf513ef1,0xbf093f5cbf7f3f6d,0x3f77bf3e3eb83dc9,0x3f6abf803f5fbf0e,0xbf273e793e60bf22,0xbf7c3f4ebee60000,0x3dfb3eacbf393f75,
0xbf803f67bf1d3e48,0x3ea13e16bf133f62,0x3f58bf043d973ec4,0x3e89bf2c3f6fbf7f,0xbecfbd493efcbf55,0xbf423f78bf7a3f46,0xbe2f3f18bf653f80,0x3f7ebf713f31be95,
0xbdc93f0ebf623f80,0x3f75bf7b3f46bec4,0xbf223e483e95bf35,0xbef13f55bf7f3f6d,0x3f7fbf553ef10000,0xbe95be483f22bf6d,0xbf463f7bbf753f35,0x3f62bf0e3dc93ec4,
0x3f7fbf553ef18000,0xbe95be483f22bf6d,0xbf463f7bbf753f35,0x3f62bf0e3dc93ec4,0x3dc9bf0e3f62bf80,0xbf753f7bbf463ec4,0x3f22be48be953f35,0x3ef1bf553f7fbf6d,
0xbf133f67bf7f3f55,0x3f7ebf4e3ecf3dc9,0x3f80bf5c3efc0000,0xbee6bd493f09bf62,0x3f7abf3e3ea13e48,0xbe89be793f31bf75,0xbeb8be163f1dbf6d,0xbf273f71bf7c3f46,
0x3f51bedbbd973f0e,0x3dfbbf183f6abf7f,0x3cc9bf043f5fbf80,0xbf653f80bf583ef1,0x3e60bf2c3f73bf7b,0xbf773f78bf393e95,0xbf6f3f7dbf4a3ec4,0x3f42beacbe2f3f22,
0xbf2c3f75bf783f35,0x3f7dbf463eac3e48,0xbedbbdc93f18bf6d,0xbf043f62bf803f55,0xbd49bef13f5cbf80,0xbf4e3f7fbf673f0e,0x3f71bf223e163ec4,0xbe79be953f3ebf7b,
0x3f3ebe95be793f35,0x3e16bf223f71bf7b,0xbf673f7fbf4e3ec4,0x3f5cbef1bd493f0e,0xbf803f62bf048000,0x3f18bdc9bedb3f55,0x3eacbf463f7dbf6d,0xbf783f75bf2c3e48,
0xbee63f5cbf803f55,0x3f7abf713f1dbdc9,0x3f77bf2c3e2f3ec4,0xbecfbe163f27bf75,0x3d97bf183f6fbf7b,0xbf513f80bf5f3ef1,0xbf7e3f67bf090000,0x3f39be79bea13f46,
0x3f65bf04bcc93f0e,0xbe60beac3f4abf7f,0x3e89bf3e3f7cbf6d,0xbf6a3f7dbf423e95,0xbf7f3f4ebeb8be48,0x3f13bd49befc3f62,0x3dfb3edbbf583f80,0x3f31bf783f73bf22,
0x3e483ec4bf553f80,0x3f0ebf6d3f7bbf35,0xbf7b3f6dbf0e0000,0x3f55bec4be483f35,0xbe48bec43f55bf80,0xbf0e3f6dbf7b3f35,0x3f7bbf6d3f0e0000,0xbf553ec43e48bf35,
0x3f7bbf6d3f0e8000,0xbf553ec43e48bf35,0x3e483ec4bf553f80,0x3f0ebf6d3f7bbf35,0xbf7b3f6dbf0e8000,0x3f55bec4be483f35,0xbe48bec43f55bf80,0xbf0e3f6dbf7b3f35,
0x3ee63e16bf313f7b,0x3e60bf3e3f7ebf62,0x3f77bf713f130000,0xbf6a3f043d97bf22,0xbf423e793eb8bf55,0x3e2f3edbbf5f3f7f,0xbf4a3f80bf583ec4,0x3f80bf4e3ea13e95,
0x3f65bf7d3f39be48,0xbf7a3f2cbdfbbef1,0xbe89beac3f51bf80,0xbecf3f5cbf7f3f46,0xbf273f78bf6f3f0e,0x3f7cbf673efc3dc9,0x3f1dbd49bf093f6d,0x3cc9bf183f73bf75,
0x3f67bef1be163f35,0xbf04bdc93f2cbf7b,0xbd493f22bf783f6d,0x3f18bf753f71bf0e,0xbeacbe953f4ebf80,0xbe793f46bf803f55,0x3f3ebf7f3f5cbec4,0xbf7d3f62bedbbe48,
0x3edbbf623f7dbf35,0xbf5c3f7fbf3e3e48,0x3f80bf463e793ec4,0xbf4e3e953eacbf55,0xbf713f75bf188000,0x3f78bf223d493f0e,0xbf2c3dc93f04bf6d,0x3e163ef1bf673f7b,
0x3f51bf803f42be48,0xbf7e3f5cbeb8be95,0xbcc9bf183f77bf6d,0xbee63f67bf7a3f22,0xbf583eac3ea1bf55,0x3efc3e16bf393f7f,0xbf6a3f78bf1d0000,0x3f7fbf3e3e2f3ef1,
0xbf13bd493f27bf7b,0x3dfb3f04bf6f3f75,0xbf803f4ebe89bec4,0x3f65bedbbe603f46,0xbf093f71bf733f0e,0x3f5fbf7d3f31bdc9,0x3ecf3e79bf4a3f80,0x3d97bf2c3f7cbf62,
0x3ef13e48bf463f80,0xbdc9bf0e3f75bf6d,0xbe953f55bf7f3f35,0x3f22bf7b3f62bec4,0xbf623f7bbf220000,0x3f7fbf553e953ec4,0xbf753f0e3dc9bf35,0x3f46be48bef13f6d,
0x3f62bf7b3f228000,0xbf7f3f55be95bec4,0x3f75bf0ebdc93f35,0xbf463e483ef1bf6d,0x3ef13e48bf463f80,0xbdc9bf0e3f75bf6d,0xbe953f55bf7f3f35,0x3f22bf7b3f62bec4,
0x3f80bf3e3dfb3f0e,0xbf733f043e2fbf46,0x3f58bf7d3f270000,0xbf773f67becfbe95,0x3eb83eacbf5f3f7b,0xbd97bf183f7abf62,0x3f51be79bee63f6d,0xbf1dbd493f31bf7f,
0x3cc9bf2c3f7ebf55,0xbea13f5cbf7c3f22,0xbf09be163f42bf80,0x3e893edbbf6a3f75,0x3f6fbf713efc3e48,0xbf7f3f4ebe60bef1,0x3f13bf783f65bec4,0xbf4a3f80bf393dc9,
0x3e16bf463f80bf35,0xbeac3f62bf783f0e,0x3f04bf753f67bec4,0xbf2c3f7fbf4e3e48,0xbf18bdc93f3ebf80,0x3edb3e95bf5c3f7b,0xbe79bef13f71bf6d,0x3d493f22bf7d3f55,
0xbf7d3f223d49bf35,0x3f71bef1be793f55,0xbf5c3e953edbbf6d,0x3f3ebdc9bf183f7b,0xbf4e3f7fbf2c8000,0x3f67bf753f043e48,0xbf783f62beacbec4,0x3f80bf463e163f0e,
0xbf7e3f4ebe2fbf0e,0x3f80bf3e3d973f22,0xbf733f67beb8bec4,0x3f7abf5c3e893ef1,0xbf5f3f78bf09be48,0x3f6abf713ee63e95,0xbf423f80bf310000,0x3f51bf7d3f1d3dc9,
0x3dfb3f18bf7c3f55,0xbcc9bf2c3f7fbf46,0x3ea13edbbf6f3f6d,0xbe60bf043f77bf62,0x3efc3e79bf583f7b,0xbecfbeac3f65bf75,0x3f273d49bf393f80,0xbf13be163f4abf7f,
0xbf3500003f353f80,0x3f350000bf35bf80,0xbf3500003f353f80,0x3f350000bf35bf80,0xbf3500003f353f80,0x3f350000bf35bf80,0xbf3500003f353f80,0x3f350000bf35bf80,
0xbf35bf80bf358000,0x3f353f803f358000,0xbf35bf80bf358000,0x3f353f803f358000,0xbf35bf80bf358000,0x3f353f803f358000,0xbf35bf80bf358000,0x3f353f803f358000,
0x3f5fbf5c3f58bf55,0x3f6abf673f65bf62,0x3f42bf3e3f39bf35,0x3f51bf4e3f4abf46,0x3f7ebf7d3f7cbf7b,0x3f80bf803f7fbf7f,0x3f73bf713f6fbf6d,0x3f7abf783f77bf75,
0x3efcbf043f09bf0e,0x3ecfbedb3ee6bef1,0x3f27bf2c3f31bf35,0x3f13bf183f1dbf22,0x3dfbbe163e2fbe48,0x3cc9bd493d97bdc9,0x3ea1beac3eb8bec4,0x3e60be793e89be95,
0xbf4e3f46bf3e3f35,0xbf673f62bf5c3f55,0xbf783f75bf713f6d,0xbf803f7fbf7d3f7b,0xbe163dc9bd490000,0xbeac3e95be793e48,0xbf043ef1bedb3ec4,0xbf2c3f22bf183f0e,
0xbf183f22bf2c3f35,0xbedb3ef1bf043f0e,0xbe793e95beac3ec4,0xbd493dc9be163e48,0xbf7d3f7fbf803f80,0xbf713f75bf783f7b,0xbf5c3f62bf673f6d,0xbf3e3f46bf4e3f55,
0x3f6fbf673f5fbf55,0x3f7fbf7d3f7abf75,0x3f13bf043ee6bec4,0x3f4abf3e3f31bf22,0x3cc93d49bdfb3e48,0x3ea1be793e2fbdc9,0xbf093f18bf273f35,0xbe893eacbecf3ef1,
0x3eb8bedb3efcbf0e,0x3d97be163e60be95,0x3f51bf5c3f65bf6d,0x3f1dbf2c3f39bf46,0x3f80bf803f7ebf7b,0x3f73bf783f7cbf7f,0x3f58bf4e3f42bf35,0x3f77bf713f6abf62,
0x3f75bf7b3f7fbf80,0x3f46bf553f62bf6d,0x3ef1bf0e3f22bf35,0x3dc9be483e95bec4,0xbe953e48bdc90000,0xbf223f0ebef13ec4,0xbf623f55bf463f35,0xbf7f3f7bbf753f6d,
0xbe953e48bdc98000,0xbf223f0ebef13ec4,0xbf623f55bf463f35,0xbf7f3f7bbf753f6d,0xbf753f7bbf7f3f80,0xbf463f55bf623f6d,0xbef13f0ebf223f35,0xbdc93e48be953ec4,
0xbf583f67bf733f7b,0xbefc3f18bf313f46,0xbf6a3f5cbf4a3f35,0xbf7f3f80bf7c3f75,0x3f51bf3e3f27bf0e,0x3f7ebf783f6fbf62,0xbcc93e16be893ec4,0x3ee6beac3e60bdc9,
0x3f09bedb3ea1be48,0x3f5fbf4e3f39bf22,0xbecf3f04bf1d3f35,0x3d973d49be2f3e95,0x3f13bf2c3f42bf55,0x3dfbbe793eb8bef1,0x3f80bf7d3f77bf6d,0x3f65bf713f7abf7f,
0x3eacbef13f18bf35,0xbe793dc93d49be48,0xbf3e3f22bf043ec4,0xbf7d3f75bf673f55,0x3edbbe953e160000,0x3f5cbf463f2cbf0e,0x3f80bf7f3f78bf6d,0x3f4ebf623f71bf7b,
0xbf713f62bf4e3f35,0xbf783f7fbf803f7b,0xbf2c3f46bf5c3f6d,0xbe163e95bedb3f0e,0x3f67bf753f7dbf80,0x3f04bf223f3ebf55,0xbd49bdc93e79bec4,0xbf183ef1beac3e48,
0x3f27bf043eb8be48,0x3f7cbf713f5fbf46,0xbf1d3f3ebf583f6d,0x3cc93e16bea13ef1,0xbf653f4ebf313f0e,0xbf7a3f80bf7e3f75,0x3e89bedb3f13bf35,0xbecf3e79bd97bdc9,
0x3f42bf5c3f6fbf7b,0x3e2fbeac3efcbf22,0x3f4abf2c3f09bec4,0x3f80bf7d3f73bf62,0xbee63f18bf393f55,0x3e60bd49bdfb3e95,0xbf773f67bf513f35,0xbf6a3f78bf7f3f7f,
0xbf553f6dbf7b3f80,0xbe483ec4bf0e3f35,0x3f0ebec43e480000,0x3f7bbf6d3f55bf35,0x3f55bf6d3f7bbf80,0x3e48bec43f0ebf35,0xbf0e3ec4be480000,0xbf7b3f6dbf553f35,
0x3f0ebec43e488000,0x3f7bbf6d3f55bf35,0x3f55bf6d3f7bbf80,0x3e48bec43f0ebf35,0xbf0e3ec4be488000,0xbf7b3f6dbf553f35,0xbf553f6dbf7b3f80,0xbe483ec4bf0e3f35,
0xbd97be163eb8bf0e,0xbf513f2cbefc3e95,0x3f7ebf713f58bf35,0x3f39bf5c3f73bf7f,0x3ee6be793cc93e48,0x3f7abf673f4abf22,0xbf773f80bf7c3f6d,0xbecf3f18bf423f62,
0xbf7f3f7dbf6f3f55,0xbf133f3ebf5f3f75,0x3dfbbeac3f09bf35,0xbf313f04bea13dc9,0x3f65bf783f80bf7b,0x3e60bedb3f1dbf46,0x3e89bd49be2f3ec4,0x3f6abf4e3f27bef1,
0x3f80bf753f5cbf35,0x3f18bf463f67bf7b,0xbeac3dc93e16bec4,0xbf783f62bf3e3f0e,0xbf2c3ef1be790000,0xbf7d3f7fbf713f55,0xbedb3f22bf4e3f6d,0x3f04be953d493e48,
0x3d49be953f04bf35,0xbf4e3f22bedb3e48,0xbf713f7fbf7d3f6d,0xbe793ef1bf2c3f55,0xbf3e3f62bf783f80,0x3e163dc9beac3f0e,0x3f67bf463f18bec4,0x3f5cbf753f80bf7b,
0x3e603d49bea13f0e,0x3f77bf5c3f31bef1,0xbf6f3f4ebf1d3ec4,0xbf423f67bf7c3f7f,0x3f51bf713f7fbf7b,0xbdfbbe163ecfbf22,0x3cc93e79befc3f35,0x3f65bf3e3f09be95,
0x3f7abf803f73bf55,0x3e89bf043f39bf62,0xbeb83f18bf4a3f6d,0x3f27bedb3e2f3dc9,0xbf133eacbd97be48,0xbf7e3f7dbf6a3f46,0x3f80bf783f5fbf35,0x3ee6bf2c3f58bf75,
0x3f22bf553f75bf80,0xbef13e483dc9bec4,0xbf7f3f7bbf623f35,0xbe953f0ebf463f6d,0x3f46bf0e3e950000,0x3f62bf7b3f7fbf6d,0xbdc9be483ef1bf35,0xbf753f55bf223ec4,
0xbf463f0ebe958000,0xbf623f7bbf7f3f6d,0x3dc93e48bef13f35,0x3f75bf553f22bec4,0x3f22bf553f75bf80,0xbef13e483dc9bec4,0xbf7f3f7bbf623f35,0xbe953f0ebf463f6d,
0x3f6abf3e3efcbe48,0x3f27bf5c3f7abf7f,0xbf7c3f7dbf653f35,0xbdfb3edbbf313f62,0xbcc93eacbf1d3f55,0x3f73bf4e3f13be95,0xbf093e793d97bec4,0xbf773f80bf6f3f46,
0x3ecfbf2c3f5fbf7b,0xbf423f04be60bdc9,0x3e2f3e16bee63f35,0x3f7ebf673f39bef1,0x3f80bf713f4abf0e,0x3ea1bf183f51bf75,0xbf583f78bf7f3f6d,0x3e893d49beb83f22,
0x3e793dc9bedb3f35,0x3f80bf753f4ebf0e,0x3e16bef13f3ebf6d,0xbf713f46bf043e48,0x3f5cbf223eac0000,0x3f2cbf623f7dbf7b,0xbf183e953d49bec4,0xbf673f7fbf783f55,
0x3f78bf7f3f67bf35,0xbd49be953f18bf55,0xbf7d3f62bf2c3ec4,0xbeac3f22bf5c3f7b,0x3f04bf463f71bf80,0xbf3e3ef1be16be48,0xbf4e3f75bf803f6d,0x3edbbdc9be793f0e,
0xbe893f18bf583f7b,0x3f6fbf3e3ee6bdc9,0x3d97bedb3f39bf6d,0xbf7c3f5cbf1d3e95,0x3dfb3e79bf133f55,0x3f80bf713f42bef1,0xbea1bd493ecfbf35,0xbf7a3f7dbf5f3f22,
0x3f77bf4e3f09be48,0x3eb8bf2c3f65bf7f,0xbf7f3f67bf313ec4,0xbe2f3f04bf4a3f75,0x3f7ebf783f51bf0e,0xbcc9beac3f27bf62,0xbf733f80bf6a3f35,0x3e603e16befc3f46,
0xbec43f35bf6d3f80,0x3f6dbf353ec40000,0x3ec4bf353f6dbf80,0xbf6d3f35bec40000,0xbec43f35bf6d3f80,0x3f6dbf353ec40000,0x3ec4bf353f6dbf80,0xbf6d3f35bec40000,
0x3f6dbf353ec48000,0x3ec4bf353f6dbf80,0xbf6d3f35bec48000,0xbec43f35bf6d3f80,0x3f6dbf353ec48000,0x3ec4bf353f6dbf80,0xbf6d3f35bec48000,0xbec43f35bf6d3f80,
0xbf4a3f78bf7c3f55,0x3f31beacbd973ef1,0x3f65bf803f6fbf35,0xbf093e163e89bf22,0xbefc3f4ebf7a3f7b,0x3f6abf2c3ea13dc9,0x3f27bf673f80bf6d,0xbf513f04bdfbbe95,
0x3f1dbe79be2f3f0e,0x3f39bf713f7fbf62,0xbee63d493eb8bf35,0xbf583f7dbf773f46,0x3f5fbf183e603e48,0x3ecfbf3e3f73bf7f,0xbf423edbbcc9bec4,0xbf133f5cbf7e3f75,
0xbf5c3f7fbf713f35,0x3f2cbe95be163f0e,0x3f18bf623f80bf6d,0xbf673f22be79be48,0xbf783f46bedb0000,0xbd493ef1bf4e3f7b,0x3f7dbf753f3ebec4,0xbeacbdc93f04bf55,
0x3f04bdc9beac3f35,0x3f3ebf753f7dbf55,0xbf4e3ef1bd49bec4,0xbedb3f46bf783f7b,0xbe793f22bf673f80,0x3f80bf623f18be48,0xbe16be953f2cbf6d,0xbf713f7fbf5c3f0e,
0xbf313f71bf7e3f55,0x3f65bf183e2f3e95,0x3f7abf783f42bec4,0xbefc3d493ecfbf46,0xbf6f3f2cbe89be48,0xbd973f04bf583f7f,0x3f13be16bea13f35,0x3f1dbf673f80bf62,
0x3f39beacbdfb3f0e,0x3ee6bf4e3f7cbf75,0xbe60be793f27bf6d,0xbf5f3f80bf6a3f22,0xbeb83f3ebf773f7b,0x3f7fbf5c3f09bdc9,0x3f51bf7d3f73bf35,0xbf4a3edb3cc9bef1,
0x3dc9bf0e3f62bf80,0xbf753f7bbf463ec4,0x3f22be48be953f35,0x3ef1bf553f7fbf6d,0xbf7f3f55bef10000,0x3e953e48bf223f6d,0x3f46bf7b3f75bf35,0xbf623f0ebdc9bec4,
0xbf7f3f55bef18000,0x3e953e48bf223f6d,0x3f46bf7b3f75bf35,0xbf623f0ebdc9bec4,0xbdc93f0ebf623f80,0x3f75bf7b3f46bec4,0xbf223e483e95bf35,0xbef13f55bf7f3f6d,
0xbe2fbeac3f42bf7b,0xbf4a3f7dbf6f3f22,0xbf393f78bf773f35,0x3f73bf2c3e603e95,0xbf583f80bf653f0e,0x3f5fbf043cc93ef1,0x3f6abf183dfb3ec4,0xbd97bedb3f51bf7f,
0xbf7c3f71bf273e48,0x3f1dbe16beb83f46,0x3f31be79be893f35,0x3ea1bf3e3f7abf75,0x3f09bd49bee63f55,0x3efcbf5c3f80bf62,0x3ecfbf4e3f7ebf6d,0xbf7f3f67bf133dc9,
0xbf3e3e953e79bf35,0xbe163f22bf713f7b,0x3f67bf7f3f4ebec4,0xbf5c3ef13d49bf0e,0x3f80bf623f040000,0xbf183dc93edbbf55,0xbeac3f46bf7d3f6d,0x3f78bf753f2cbe48,
0xbf2c3f75bf783f35,0x3f7dbf463eac3e48,0xbedbbdc93f18bf6d,0xbf043f62bf803f55,0xbd49bef13f5cbf80,0xbf4e3f7fbf673f0e,0x3f71bf223e163ec4,0xbe79be953f3ebf7b,
0xbf733f78bf313e48,0x3f58bedbbdfb3f22,0x3efc3d49bf133f6d,0x3eb8bf4e3f7fbf62,0x3f42bf7d3f6abf0e,0xbf7c3f3ebe89be95,0xbf4a3eac3e60bf35,0x3cc93f04bf653f7f,
0x3ea13e79bf393f7b,0x3f09bf673f7ebf46,0x3f5fbf803f51bec4,0xbf6f3f18bd97bef1,0xbf273e163ecfbf55,0xbe2f3f2cbf773f75,0xbf1d3f71bf7a3f35,0x3f80bf5c3ee63dc9,
0x3e483ec4bf553f80,0x3f0ebf6d3f7bbf35,0xbf7b3f6dbf0e0000,0x3f55bec4be483f35,0xbe48bec43f55bf80,0xbf0e3f6dbf7b3f35,0x3f7bbf6d3f0e0000,0xbf553ec43e48bf35,
0x3f7bbf6d3f0e8000,0xbf553ec43e48bf35,0x3e483ec4bf553f80,0x3f0ebf6d3f7bbf35,0xbf7b3f6dbf0e8000,0x3f55bec4be483f35,0xbe48bec43f55bf80,0xbf0e3f6dbf7b3f35,
0x3f73bf183cc93f0e,0xbf09bd493f1dbf75,0x3efcbf673f7cbf35,0xbf6f3f78bf273dc9,0xbf7f3f5cbecfbe48,0x3f51beacbe893f46,0xbdfb3f2cbf7a3f6d,0x3f39bf7d3f65bef1,
0x3ea1bf4e3f80bf55,0xbf583f80bf4a3e95,0xbf5f3edb3e2fbf35,0x3eb83e79bf423f7f,0x3d973f04bf6a3f7b,0x3f13bf713f77bf22,0x3f7ebf3e3e603ec4,0xbf313e163ee6bf62,
0x3edbbf623f7dbf35,0xbf5c3f7fbf3e3e48,0x3f80bf463e793ec4,0xbf4e3e953eacbf55,0xbf713f75bf180000,0x3f78bf223d493f0e,0xbf2c3dc93f04bf6d,0x3e163ef1bf673f7b,
0xbf673ef13e16bf35,0x3f043dc9bf2c3f7b,0x3d49bf223f78bf6d,0xbf183f75bf713f0e,0x3eac3e95bf4e3f80,0x3e79bf463f80bf55,0xbf3e3f7fbf5c3ec4,0x3f7dbf623edb3e48,
0xbf7c3f2cbd97bf0e,0x3f4abe79becf3f62,0xbf313f7dbf5f3ec4,0x3f73bf713f093dc9,0x3e603edbbf653f7b,0x3e89bf4e3f80bf46,0x3f6fbf04bdfb3f35,0xbf273d493f13bf75,
0xbe2f3f3ebf7f3f55,0x3f1dbf783f6abef1,0x3f39be16befc3f6d,0xbea1beac3f58bf7f,0x3f7abf673ee63e48,0xbf773f183cc9bf22,0x3eb8bf5c3f7ebf35,0xbf423f80bf513e95,
0xbef1be483f46bf80,0x3dc93f0ebf753f6d,0x3e95bf553f7fbf35,0xbf223f7bbf623ec4,0x3f62bf7b3f220000,0xbf7f3f55be95bec4,0x3f75bf0ebdc93f35,0xbf463e483ef1bf6d,
0xbf623f7bbf228000,0x3f7fbf553e953ec4,0xbf753f0e3dc9bf35,0x3f46be48bef13f6d,0xbef1be483f46bf80,0x3dc93f0ebf753f6d,0x3e95bf553f7fbf35,0xbf223f7bbf623ec4,
0xbf393f80bf4a3e48,0x3f65bf783f133dc9,0xbe603f4ebf7f3f35,0x3efcbf713f6fbef1,0xbf6a3edb3e89bf55,0x3f42be16bf093f75,0xbf7c3f5cbea1bec4,0x3f7ebf2c3cc93f22,
0x3f31bd49bf1d3f7b,0xbee6be793f51bf7f,0x3f7abf18bd973f35,0xbf5f3eac3eb8bf62,0xbecf3f67bf773f0e,0x3f27bf7d3f58be95,0x3e2f3f04bf733f6d,0x3dfbbf3e3f80bf46,
0x3f7dbf22bd493f35,0xbf713ef13e79bf55,0x3f5cbe95bedb3f6d,0xbf3e3dc93f18bf7b,0x3f4ebf7f3f2c0000,0xbf673f75bf04be48,0x3f78bf623eac3ec4,0xbf803f46be16bf0e,
0x3e16bf463f80bf35,0xbeac3f62bf783f0e,0x3f04bf753f67bec4,0xbf2c3f7fbf4e3e48,0xbf18bdc93f3ebf80,0x3edb3e95bf5c3f7b,0xbe79bef13f71bf6d,0x3d493f22bf7d3f55,
0xbf4a3e163f13bf7b,0x3f39bd49bf273f7f,0xbf653eac3ecfbf6d,0x3f58be79befc3f75,0xbf773f043e60bf55,0x3f6fbedbbea13f62,0xbf7f3f2c3cc9bf35,0x3f7cbf18bdfb3f46,
0xbf1d3f7dbf513e48,0x3f31bf803f42bdc9,0xbee63f71bf6a3ec4,0x3f09bf783f5fbe95,0xbe893f5cbf7a3f0e,0x3eb8bf673f73bef1,0xbd973f3ebf803f35,0x3e2fbf4e3f7ebf22,
0x3f350000bf353f80,0xbf3500003f35bf80,0x3f350000bf353f80,0xbf3500003f35bf80,0x3f350000bf353f80,0xbf3500003f35bf80,0x3f350000bf353f80,0xbf3500003f35bf80,
0xbf353f80bf358000,0x3f35bf803f358000,0xbf353f80bf358000,0x3f35bf803f358000,0xbf353f80bf358000,0x3f35bf803f358000,0xbf353f80bf358000,0x3f35bf803f358000,
0xbf773e793f7abe48,0xbf6f3eac3f73be95,0xbf7f3d493f800000,0xbf7c3e163f7ebdc9,0xbf4a3f183f51bf0e,0xbf393f2c3f42bf22,0xbf653edb3f6abec4,0xbf583f043f5fbef1,
0x3e893f78be60bf7b,0x3eb83f71bea1bf75,0x3d973f80bcc9bf80,0x3e2f3f7dbdfbbf7f,0x3f1d3f4ebf13bf55,0x3f313f3ebf27bf46,0x3ee63f67becfbf6d,0x3f093f5cbefcbf62,
0x3f4e3f22bf3ebf35,0x3f673ef1bf5cbf0e,0x3f783e95bf71bec4,0x3f803dc9bf7dbe48,0x3e163f7fbd49bf80,0x3eac3f75be79bf7b,0x3f043f62bedbbf6d,0x3f2c3f46bf18bf55,
0x3f18bf46bf2c3f35,0x3edbbf62bf043f55,0x3e79bf75beac3f6d,0x3d49bf7fbe163f7b,0x3f7dbdc9bf808000,0x3f71be95bf783e48,0x3f5cbef1bf673ec4,0x3f3ebf22bf4e3f0e,
0xbecfbf713e893f7b,0xbf27bf4e3f093f62,0x3e2fbf78bea13f6d,0xbdfbbf80bcc93f7f,0x3f31bf2cbf4a3f0e,0x3ee6bf5cbf133f46,0x3f7abe16bf7f0000,0x3f5fbedbbf6f3e95,
0xbf6a3eac3f77be48,0xbf423f183f58bef1,0xbf7cbe793f733ec4,0xbf7e3d493f803dc9,0xbf39bf3e3f1d3f55,0xbf65bf043f513f22,0xbe60bf7d3d973f80,0xbefcbf673eb83f75,
0xbe95bf7b3dc93f80,0xbf22bf553ef13f6d,0xbf62bf0e3f463f35,0xbf7fbe483f753ec4,0xbf753e483f7f0000,0xbf463f0e3f62bec4,0xbef13f553f22bf35,0xbdc93f7b3e95bf6d,
0xbf753e483f7f8000,0xbf463f0e3f62bec4,0xbef13f553f22bf35,0xbdc93f7b3e95bf6d,0x3e953f7bbdc9bf80,0x3f223f55bef1bf6d,0x3f623f0ebf46bf35,0x3f7f3e48bf75bec4,
0xbe603f713ee6bf55,0x3e893f7dbcc9bf7f,0xbf6f3e793f7e0000,0xbf273f2c3f51bef1,0x3f7cbd49bf7fbe48,0x3f4abf04bf6a3e95,0x3f313f4ebefcbf6d,0x3f733edbbf58bf22,
0x3f7a3eacbf65bf0e,0x3f77be16bf80bdc9,0x3eb83f78bdfbbf80,0x3f423f3ebf13bf62,0xbe2fbf80bd973f7b,0xbf1dbf5c3ecf3f75,0x3f39bf18bf5f3ec4,0x3ea1bf67bf093f46,
0x3eacbf62bf183f35,0xbe79bf7fbd493f7b,0xbf3ebf463f043f6d,0xbf7dbe953f673f0e,0x3edb3f75be16bf80,0x3f5c3f22bf2cbf55,0x3f803dc9bf78bec4,0x3f4ebef1bf713e48,
0xbf71bef13f4e3f35,0xbf783dc93f803e48,0xbf2c3f223f5cbec4,0xbe163f753edbbf55,0x3f67be95bf7d8000,0x3f04bf46bf3e3f0e,0xbd49bf7fbe793f6d,0xbf18bf623eac3f7b,
0xbd973f783ecfbf55,0x3f133f67be89bf7f,0xbf7ebd493f7a3ec4,0xbf313f183f65be95,0xbea1bf7dbcc93f7b,0xbf58bf2c3f1d3f62,0x3f5fbeacbf7c0000,0x3eb8bf5cbf273f22,
0x3f7f3e79bf6abf0e,0x3f51bedbbf773dc9,0x3dfb3f803e60bf6d,0x3f393f4ebee6bf75,0xbf733e163f803e48,0xbf093f3e3f4abef1,0xbefcbf713e2f3f80,0xbf6fbf043f423f46,
0xbf0ebf6d3e483f80,0xbf7bbec43f553f35,0xbf553ec43f7b0000,0xbe483f6d3f0ebf35,0x3f0e3f6dbe48bf80,0x3f7b3ec4bf55bf35,0x3f55bec4bf7b0000,0x3e48bf6dbf0e3f35,
0xbf553ec43f7b8000,0xbe483f6d3f0ebf35,0x3f0e3f6dbe48bf80,0x3f7b3ec4bf55bf35,0x3f55bec4bf7b8000,0x3e48bf6dbf0e3f35,0xbf0ebf6d3e483f80,0xbf7bbec43f553f35,
0x3f423f4ebecfbf7b,0x3f7c3d49bf77bef1,0xbf4a3edb3f7a0000,0xbcc93f783ee6bf46,0xbf73bf043f393f55,0xbf583eac3f7e3dc9,0x3efcbf3ebf513ec4,0xbeb8bf7dbd973f75,
0x3f27bf18bf6a3e48,0xbe2fbf80be893f62,0x3f1d3f67be60bf80,0x3f803e79bf65bf22,0xbea13f5c3f31bf0e,0x3f093f71bdfbbf7f,0xbf5fbf2c3f133f6d,0xbf6f3e163f7f3e95,
0xbf80be953f5c3f35,0xbf183f223f67be48,0x3eac3f7f3e16bf6d,0x3f783ef1bf3ebf55,0x3f2c3f62be79bf80,0x3f7d3dc9bf71bf0e,0x3edbbf46bf4e3ec4,0xbf04bf753d493f7b,
0xbd493f753f04bf35,0x3f4e3f46bedbbf7b,0x3f71bdc9bf7dbec4,0x3e79bf62bf2c3f0e,0x3f3ebef1bf788000,0xbe16bf7fbeac3f55,0xbf67bf223f183f6d,0xbf5c3e953f803e48,
0x3f09bf2cbf653e48,0xbefcbf78bcc93f75,0x3ecf3f7d3dfbbf6d,0x3f7f3eacbf51bf46,0xbf7cbedb3f423f55,0xbf1d3f183f6fbdc9,0x3f31bf04bf770000,0xbea1bf80be603f62,
0xbf58bf3e3ee63f7b,0xbf5f3e793f803e95,0x3f6abe16bf7ebec4,0x3d97bf71bf133f22,0xbe2f3f673f27bf0e,0x3f4a3f4ebeb8bf7f,0xbf39bf5c3e893f80,0xbf733d493f7a3ef1,
0xbf46bf553e953f80,0xbf623e483f7f3ec4,0x3dc93f7b3ef1bf35,0x3f753f0ebf22bf6d,0x3f22bf0ebf750000,0xbef1bf7bbdc93f6d,0xbf7fbe483f623f35,0xbe953f553f46bec4,
0xbf223f0e3f758000,0x3ef13f7b3dc9bf6d,0x3f7f3e48bf62bf35,0x3e95bf55bf463ec4,0xbf46bf553e953f80,0xbf623e483f7f3ec4,0x3dc93f7b3ef1bf35,0x3f753f0ebf22bf6d,
0x3f6fbd49bf77bf0e,0xbd97bf78bf093f22,0xbf133f183f730000,0x3f1d3f71bcc9bf75,0x3f313f67bdfbbf7b,0x3f65be16bf7cbef1,0xbf7abf043f273f6d,0xbefc3f2c3f6abdc9,
0xbeb8bf80be893f55,0xbf7fbe793f583f46,0x3f513f4ebea1bf80,0x3f4abeacbf80be95,0x3f39bedbbf7ebe48,0xbee6bf7dbe2f3f62,0xbe603f5c3f42bec4,0x3f5f3f3ebecfbf7f,
0x3e793f7f3edbbf35,0x3f803e95bf4ebf55,0x3e16bf62bf3e3ec4,0xbf71bf223f043f7b,0x3f5c3f46beacbf80,0x3f2cbef1bf7dbe48,0xbf18bf75bd493f6d,0xbf673dc93f783f0e,
0x3f783dc9bf67bf35,0xbd49bf75bf183f0e,0xbf7dbef13f2c3f6d,0xbeac3f463f5cbe48,0x3f04bf22bf718000,0xbf3ebf623e163f7b,0xbf4e3e953f803ec4,0x3edb3f7f3e79bf55,
0xbf5f3e163f7a3f0e,0x3ecf3f803ea1bf46,0x3f42beacbf80bec4,0xbf13bf78bdfb3f62,0xbf1d3f043f7c3e48,0x3f393f67bd97bf75,0x3ee6bf2cbf6f0000,0xbf58bf4e3e893f7f,
0x3efc3f7d3e60bf55,0x3f6abd49bf73bf22,0xbf27bf71bcc93f6d,0xbf513e793f7e3ef1,0x3f4a3f5cbe2fbf7b,0x3f31bedbbf7fbe95,0xbf65bf3e3eb83f80,0xbf093f183f773dc9,
0xbf6dbf353ec43f80,0xbec43f353f6d0000,0x3f6d3f35bec4bf80,0x3ec4bf35bf6d0000,0xbf6dbf353ec43f80,0xbec43f353f6d0000,0x3f6d3f35bec4bf80,0x3ec4bf35bf6d0000,
0xbec43f353f6d8000,0x3f6d3f35bec4bf80,0x3ec4bf35bf6d8000,0xbf6dbf353ec43f80,0xbec43f353f6d8000,0x3f6d3f35bec4bf80,0x3ec4bf35bf6d8000,0xbf6dbf353ec43f80,
0x3dfbbf5cbf513e48,0xbf80bedb3f273f75,0xbea13f3e3f6a0000,0x3f7a3f18befcbf7f,0xbe89bf7dbf093f0e,0xbf6fbd493f653f46,0x3d973f713f31bec4,0x3f7c3e79bf4abf62,
0xbf7ebf043f133f7b,0xbcc93f673f42be95,0x3f733f2cbecfbf80,0x3e60bf4ebf5f3dc9,0xbf77be163f583f55,0x3eb83f803ee6bf22,0x3f7f3eacbf39bf6d,0xbe2fbf78bf1d3ef1,
0x3f5cbdc9bf71bf35,0xbf2cbf75be163f55,0xbf183ef13f803ec4,0x3f673f46be79bf7b,0x3f783f22bedbbf80,0x3d49bf62bf4e3e48,0xbf7dbe953f3e3f6d,0x3eac3f7f3f04bf0e,
0xbf04bf7fbeac3f35,0xbf3e3e953f7d3f0e,0x3f4e3f62bd49bf6d,0x3edbbf22bf78be48,0x3e79bf46bf678000,0xbf80bef13f183f7b,0x3e163f753f2cbec4,0x3f713dc9bf5cbf55,
0x3f803edbbf1dbf7b,0xbea1bf7dbf133ef1,0xbf58bf5c3d973f6d,0xbe893f3e3f6f3dc9,0x3ecf3f803efcbf0e,0x3f42be79bf7abf22,0x3e2fbf4ebf650000,0xbf7ebeac3f313f75,
0xbcc9bf67bf4a3e48,0xbf73be163f513f62,0xbf093f043f7f3ec4,0x3f773f2cbeb8bf7f,0x3f6a3d49bf5fbf55,0xbf27bf78be603f46,0xbf7cbf183ee63f80,0x3dfb3f713f39be95,
0xbf7fbf0e3ef13f80,0x3e953f7b3f22bec4,0x3f46be48bf75bf35,0xbf62bf553dc93f6d,0xbdc93f553f620000,0x3f753e48bf46bf6d,0xbf22bf7bbe953f35,0xbef13f0e3f7f3ec4,
0xbdc93f553f628000,0x3f753e48bf46bf6d,0xbf22bf7bbe953f35,0xbef13f0e3f7f3ec4,0x3f7f3f0ebef1bf80,0xbe95bf7bbf223ec4,0xbf463e483f753f35,0x3f623f55bdc9bf6d,
0xbf51bf67bd973f55,0xbdfb3f4e3f6a3dc9,0xbcc93f5c3f5f0000,0x3f653d49bf58bf62,0xbe603f3e3f733e48,0x3f773e79bf39bf75,0x3f6f3e16bf4abf6d,0xbf42bf71be2f3f46,
0xbf133edb3f7f3f0e,0x3f7e3f18becfbf7f,0x3f803f04befcbf80,0xbee6bf80bf093ef1,0x3f7a3f2cbea1bf7b,0xbe89bf78bf313e95,0xbeb8bf7dbf1d3ec4,0xbf273eac3f7c3f22,
0xbf3ebf75be793f35,0xbe163f463f713e48,0x3f673dc9bf4ebf6d,0xbf5cbf62bd493f55,0x3f803ef1bf04bf80,0xbf18bf7fbedb3f0e,0xbeac3f223f7d3ec4,0x3f783e95bf2cbf7b,
0xbf2c3e953f783f35,0x3f7d3f22beacbf7b,0xbedbbf7fbf183ec4,0xbf043ef13f803f0e,0xbd49bf62bf5c8000,0xbf4e3dc93f673f55,0x3f713f46be16bf6d,0xbe79bf75bf3e3e48,
0xbf65bf5cbcc93f55,0x3e603f713f4abdc9,0xbe893f2c3f7c3ec4,0x3f6a3e16bf42bf75,0x3f7f3f18beb8bf7b,0xbf13bf80befc3ef1,0xbdfbbf67bf580000,0xbf313e793f733f46,
0xbee63f043f803f0e,0x3f7a3eacbf1dbf7f,0x3f773f3ebe2fbf6d,0xbecfbf7dbf273e95,0x3d97bf4ebf6fbe48,0xbf513d493f5f3f62,0xbf7ebedb3f093f80,0x3f393f783ea1bf22,
0xbf7bbec43f0e3f80,0x3f553f6d3e48bf35,0xbe48bf6dbf550000,0xbf0e3ec43f7b3f35,0x3f7b3ec4bf0ebf80,0xbf55bf6dbe483f35,0x3e483f6d3f550000,0x3f0ebec4bf7bbf35,
0x3e483f6d3f558000,0x3f0ebec4bf7bbf35,0xbf7bbec43f0e3f80,0x3f553f6d3e48bf35,0xbe48bf6dbf558000,0xbf0e3ec43f7b3f35,0x3f7b3ec4bf0ebf80,0xbf55bf6dbe483f35,
0xbf65be163f393f7b,0x3f7a3f3ebdfbbf62,0x3e893f713f510000,0x3ecfbf04bf7fbf22,0x3f27be79bf6fbf55,0xbf7cbedb3efc3f7f,0xbf1dbf80bf093ec4,0xbcc93f4e3f733e95,
0x3ee63f7d3f31be48,0x3e60bf2cbf7ebef1,0x3f773eacbf13bf80,0xbf6abf5cbd973f46,0xbf42bf78beb83f0e,0x3e2f3f673f5f3dc9,0xbf4a3d493f583f6d,0x3f803f18bea1bf75,
0xbedb3ef13f7d3f35,0x3f5c3dc9bf3ebf7b,0xbf80bf223e793f6d,0x3f4e3f753eacbf0e,0x3f713e95bf18bf80,0xbf78bf463d493f55,0x3f2c3f7f3f04bec4,0xbe16bf62bf67be48,
0x3f673f623e16bf35,0xbf04bf7fbf2c3e48,0xbd493f463f783ec4,0x3f18be95bf71bf55,0xbeacbf75bf4e8000,0xbe793f223f803f0e,0x3f3ebdc9bf5cbf6d,0xbf7dbef13edb3f7b,
0x3f133f803f27be48,0xbdfbbf5cbf6fbe95,0x3f803f18be89bf6d,0xbf65bf67be603f22,0x3f09beacbf73bf55,0xbf5fbe163f313f7f,0xbecfbf78bf4a0000,0xbd973f3e3f7c3ef1,
0x3f513d49bf42bf7b,0xbf7ebf043eb83f75,0xbcc9bf4ebf77bec4,0xbee63edb3f7a3f46,0xbf58bf71bea13f0e,0x3efc3f7d3f39bdc9,0xbf6abe793f1d3f80,0x3f7f3f2cbe2fbf62,
0xbf62be483f223f80,0x3f7f3f0ebe95bf6d,0xbf75bf55bdc93f35,0x3f463f7b3ef1bec4,0xbef1bf7bbf460000,0x3dc93f553f753ec4,0x3e95bf0ebf7fbf35,0xbf223e483f623f6d,
0x3ef13f7b3f468000,0xbdc9bf55bf75bec4,0xbe953f0e3f7f3f35,0x3f22be48bf62bf6d,0xbf62be483f223f80,0x3f7f3f0ebe95bf6d,0xbf75bf55bdc93f35,0x3f463f7b3ef1bec4,
0xbcc93f3e3f7e3f0e,0x3ea1bf04bf7cbf46,0x3f093f7d3f420000,0xbe89bf67bf6abe95,0xbf6fbeac3efc3f7b,0x3f7f3f18be60bf62,0xbf133e793f653f6d,0x3f4a3d49bf39bf7f,
0x3f803f2cbdfbbf55,0xbf73bf5cbe2f3f22,0x3f583e16bf27bf80,0xbf77bedb3ecf3f75,0x3eb83f713f5f3e48,0xbd97bf4ebf7abef1,0x3f513f783ee6bec4,0xbf1dbf80bf313dc9,
0x3f7d3f463d49bf35,0xbf71bf62be793f0e,0x3f5c3f753edbbec4,0xbf3ebf7fbf183e48,0x3f4e3dc9bf2cbf80,0xbf67be953f043f7b,0x3f783ef1beacbf6d,0xbf80bf223e163f55,
0x3e16bf22bf80bf35,0xbeac3ef13f783f55,0x3f04be95bf67bf6d,0xbf2c3dc93f4e3f7b,0xbf18bf7fbf3e8000,0x3edb3f753f5c3e48,0xbe79bf62bf71bec4,0x3d493f463f7d3f0e,
0xbdfbbf4ebf7cbf0e,0x3cc93f3e3f7f3f22,0xbea1bf67bf6fbec4,0x3e603f5c3f773ef1,0xbefcbf78bf58be48,0x3ecf3f713f653e95,0xbf27bf80bf390000,0x3f133f7d3f4a3dc9,
0xbf7ebf183e2f3f55,0x3f803f2cbd97bf46,0xbf73bedb3eb83f6d,0x3f7a3f04be89bf62,0xbf5fbe793f093f7b,0x3f6a3eacbee6bf75,0xbf42bd493f313f80,0x3f513e16bf1dbf7f,
0x3f350000bf353f80,0xbf3500003f35bf80,0x3f350000bf353f80,0xbf3500003f35bf80,0x3f350000bf353f80,0xbf3500003f35bf80,0x3f350000bf353f80,0xbf3500003f35bf80,
0xbf353f80bf358000,0x3f35bf803f358000,0xbf353f80bf358000,0x3f35bf803f358000,0xbf353f80bf358000,0x3f35bf803f358000,0xbf353f80bf358000,0x3f35bf803f358000,
0xbefc3f5c3f09bf55,0xbecf3f673ee6bf62,0xbf273f3e3f31bf35,0xbf133f4e3f1dbf46,0xbdfb3f7d3e2fbf7b,0xbcc93f803d97bf7f,0xbea13f713eb8bf6d,0xbe603f783e89bf75,
0x3f5f3f04bf58bf0e,0x3f6a3edbbf65bef1,0x3f423f2cbf39bf35,0x3f513f18bf4abf22,0x3f7e3e16bf7cbe48,0x3f803d49bf7fbdc9,0x3f733eacbf6fbec4,0x3f7a3e79bf77be95,
0x3f18bf46bf2c3f35,0x3edbbf62bf043f55,0x3e79bf75beac3f6d,0x3d49bf7fbe163f7b,0x3f7dbdc9bf800000,0x3f71be95bf783e48,0x3f5cbef1bf673ec4,0x3f3ebf22bf4e3f0e,
0xbf4ebf223f3e3f35,0xbf67bef13f5c3f0e,0xbf78be953f713ec4,0xbf80bdc93f7d3e48,0xbe16bf7f3d493f80,0xbeacbf753e793f7b,0xbf04bf623edb3f6d,0xbf2cbf463f183f55,
0xbeb83f673efcbf55,0xbd973f7d3e60bf75,0xbf513f043f65bec4,0xbf1d3f3e3f39bf22,0xbf80bd493f7e3e48,0xbf733e793f7cbdc9,0xbf58bf183f423f35,0xbf77beac3f6a3ef1,
0x3f6f3edbbf5fbf0e,0x3f7f3e16bf7abe95,0x3f133f5cbee6bf6d,0x3f4a3f2cbf31bf46,0x3cc93f803dfbbf7b,0x3ea13f78be2fbf7f,0xbf093f4e3f27bf35,0xbe893f713ecfbf62,
0x3e953f7bbdc9bf80,0x3f223f55bef1bf6d,0x3f623f0ebf46bf35,0x3f7f3e48bf75bec4,0x3f75be48bf7f0000,0x3f46bf0ebf623ec4,0x3ef1bf55bf223f35,0x3dc9bf7bbe953f6d,
0x3f75be48bf7f8000,0x3f46bf0ebf623ec4,0x3ef1bf55bf223f35,0x3dc9bf7bbe953f6d,0xbe95bf7b3dc93f80,0xbf22bf553ef13f6d,0xbf62bf0e3f463f35,0xbf7fbe483f753ec4,
0xbf09bf673ea13f7b,0xbf5fbf183f393f46,0x3ecfbf5cbf1d3f35,0xbd97bf80be2f3f75,0xbf133f3e3f42bf0e,0xbdfb3f783eb8bf62,0xbf80be163f773ec4,0xbf653eac3f7abdc9,
0xbf583edb3f73be48,0xbefc3f4e3f31bf22,0xbf6abf043f4a3f35,0xbf7fbd493f7c3e95,0x3f513f2cbf27bf55,0x3f7e3e79bf6fbef1,0xbcc93f7d3e89bf6d,0x3ee63f71be60bf7f,
0x3f713ef1bf4ebf35,0x3f78bdc9bf80be48,0x3f2cbf22bf5c3ec4,0x3e16bf75bedb3f55,0xbf673e953f7d0000,0xbf043f463f3ebf0e,0x3d493f7f3e79bf6d,0x3f183f62beacbf7b,
0x3eacbf62bf183f35,0xbe79bf7fbd493f7b,0xbf3ebf463f043f6d,0xbf7dbe953f673f0e,0x3edb3f75be16bf80,0x3f5c3f22bf2cbf55,0x3f803dc9bf78bec4,0x3f4ebef1bf713e48,
0xbf423f043f6fbe48,0xbe2f3f713efcbf46,0xbf4abf3e3f093f6d,0xbf80be163f733ef1,0x3ee6bf4ebf393f0e,0xbe60bf80bdfb3f75,0x3f773edbbf51bf35,0x3f6abe79bf7fbdc9,
0x3f273f5cbeb8bf7b,0x3f7c3eacbf5fbf22,0xbf1d3f2c3f58bec4,0x3cc93f7d3ea1bf62,0xbf65bf183f313f55,0xbf7a3d493f7e3e95,0x3e89bf67bf133f35,0xbecfbf783d973f7f,
0xbf0ebf6d3e483f80,0xbf7bbec43f553f35,0xbf553ec43f7b0000,0xbe483f6d3f0ebf35,0x3f0e3f6dbe48bf80,0x3f7b3ec4bf55bf35,0x3f55bec4bf7b0000,0x3e48bf6dbf0e3f35,
0xbf553ec43f7b8000,0xbe483f6d3f0ebf35,0x3f0e3f6dbe48bf80,0x3f7b3ec4bf55bf35,0x3f55bec4bf7b8000,0x3e48bf6dbf0e3f35,0xbf0ebf6d3e483f80,0xbf7bbec43f553f35,
0x3f7f3e16bf6fbf0e,0x3f13bf2cbf5f3e95,0xbdfb3f713f09bf35,0x3f313f5cbea1bf7f,0xbf653e793f803e48,0xbe603f673f1dbf22,0xbe89bf80be2f3f6d,0xbf6abf183f273f62,
0xbd97bf7dbeb83f55,0xbf51bf3e3efc3f75,0x3f7e3eacbf58bf35,0x3f39bf04bf733dc9,0x3ee63f78bcc9bf7b,0x3f7a3edbbf4abf46,0xbf773d493f7c3ec4,0xbecf3f4e3f42bef1,
0xbd493f753f04bf35,0x3f4e3f46bedbbf7b,0x3f71bdc9bf7dbec4,0x3e79bf62bf2c3f0e,0x3f3ebef1bf780000,0xbe16bf7fbeac3f55,0xbf67bf223f183f6d,0xbf5c3e953f803e48,
0x3f803e95bf5cbf35,0x3f18bf22bf673e48,0xbeacbf7fbe163f6d,0xbf78bef13f3e3f55,0xbf2cbf623e793f80,0xbf7dbdc93f713f0e,0xbedb3f463f4ebec4,0x3f043f75bd49bf7b,
0xbf7abd493f733f0e,0xbe893f5c3f39bef1,0x3eb8bf4ebf4a3ec4,0xbf27bf673e2f3f7f,0x3f133f71bd97bf7b,0x3f7e3e16bf6abf22,0xbf80be793f5f3f35,0xbee63f3e3f58be95,
0x3e603f803ea1bf55,0x3f773f04bf31bf62,0xbf6fbf183f1d3f6d,0xbf423edb3f7c3dc9,0x3f51beacbf7fbe48,0xbdfbbf7dbecf3f46,0x3cc93f783efcbf35,0x3f653f2cbf09bf75,
0x3f463f55be95bf80,0x3f62be48bf7fbec4,0xbdc9bf7bbef13f35,0xbf75bf0e3f223f6d,0xbf223f0e3f750000,0x3ef13f7b3dc9bf6d,0x3f7f3e48bf62bf35,0x3e95bf55bf463ec4,
0x3f22bf0ebf758000,0xbef1bf7bbdc93f6d,0xbf7fbe483f623f35,0xbe953f553f46bec4,0x3f463f55be95bf80,0x3f62be48bf7fbec4,0xbdc9bf7bbef13f35,0xbf75bf0e3f223f6d,
0xbecf3f3e3f5fbe48,0x3f423f5cbe60bf7f,0xbe2fbf7dbee63f35,0xbf7ebedb3f393f62,0xbf80beac3f4a3f55,0xbea13f4e3f51be95,0x3f58be79bf7fbec4,0xbe89bf80beb83f46,
0x3f6a3f2cbefcbf7b,0x3f27bf04bf7abdc9,0xbf7cbe163f653f35,0xbdfb3f673f31bef1,0xbcc93f713f1dbf0e,0x3f733f18bf13bf75,0xbf09bf78bd973f6d,0xbf77bd493f6f3f22,
0xbf78bdc93f673f35,0x3d493f753f18bf0e,0x3f7d3ef1bf2cbf6d,0x3eacbf46bf5c3e48,0xbf043f223f710000,0x3f3e3f62be16bf7b,0x3f4ebe95bf80bec4,0xbedbbf7fbe793f55,
0x3e793f7f3edbbf35,0x3f803e95bf4ebf55,0x3e16bf62bf3e3ec4,0xbf71bf223f043f7b,0x3f5c3f46beacbf80,0x3f2cbef1bf7dbe48,0xbf18bf75bd493f6d,0xbf673dc93f783f0e,
0xbf77bf183f093f7b,0xbeb83f3e3f65bdc9,0x3f7f3edbbf31bf6d,0x3e2fbf5cbf4a3e95,0xbf7ebe793f513f55,0x3cc93f713f27bef1,0x3f733d49bf6abf35,0xbe60bf7dbefc3f22,
0xbe893f4e3f58be48,0x3f6f3f2cbee6bf7f,0x3d97bf67bf393ec4,0xbf7cbf043f1d3f75,0x3dfb3f783f13bf0e,0x3f803eacbf42bf62,0xbea1bf80becf3f35,0xbf7abe163f5f3f46,
0xbf6dbf353ec43f80,0xbec43f353f6d0000,0x3f6d3f35bec4bf80,0x3ec4bf35bf6d0000,0xbf6dbf353ec43f80,0xbec43f353f6d0000,0x3f6d3f35bec4bf80,0x3ec4bf35bf6d0000,
0xbec43f353f6d8000,0x3f6d3f35bec4bf80,0x3ec4bf35bf6d8000,0xbf6dbf353ec43f80,0xbec43f353f6d8000,0x3f6d3f35bec4bf80,0x3ec4bf35bf6d8000,0xbf6dbf353ec43f80,
0xbf1dbf78be2f3f55,0xbf393eac3f7f3ef1,0x3ee63f803eb8bf35,0x3f58be16bf77bf22,0xbf5fbf4e3e603f7b,0xbecf3f2c3f733dc9,0x3f423f67bcc9bf6d,0x3f13bf04bf7ebe95,
0xbf4a3e793f7c3f0e,0x3f313f713d97bf62,0x3f65bd49bf6fbf35,0xbf09bf7dbe893f46,0xbefc3f183f7a3e48,0x3f6a3f3ebea1bf7f,0x3f27bedbbf80bec4,0xbf51bf5c3dfb3f75,
0xbf04bf7fbeac3f35,0xbf3e3e953f7d3f0e,0x3f4e3f62bd49bf6d,0x3edbbf22bf78be48,0x3e79bf46bf670000,0xbf80bef13f183f7b,0x3e163f753f2cbec4,0x3f713dc9bf5cbf55,
0xbf5c3dc93f713f35,0x3f2c3f753e16bf55,0x3f18bef1bf80bec4,0xbf67bf463e793f7b,0xbf78bf223edb3f80,0xbd493f623f4ebe48,0x3f7d3e95bf3ebf6d,0xbeacbf7fbf043f0e,
0xbf39bf71bdfb3f55,0xbee63f183f7c3e95,0x3e603f783f27bec4,0x3f5fbd49bf6abf46,0x3eb8bf2cbf77be48,0xbf7fbf043f093f7f,0xbf513e163f733f35,0x3f4a3f673cc9bf62,
0xbf313eac3f7e3f0e,0x3f653f4ebe2fbf75,0x3f7a3e79bf42bf6d,0xbefcbf80becf3f22,0xbf6fbf3e3e893f7b,0xbd973f5c3f58bdc9,0x3f133f7d3ea1bf35,0x3f1dbedbbf80bef1,
0x3f7f3f0ebef1bf80,0xbe95bf7bbf223ec4,0xbf463e483f753f35,0x3f623f55bdc9bf6d,0x3dc9bf55bf620000,0xbf75be483f463f6d,0x3f223f7b3e95bf35,0x3ef1bf0ebf7fbec4,
0x3dc9bf55bf628000,0xbf75be483f463f6d,0x3f223f7b3e95bf35,0x3ef1bf0ebf7fbec4,0xbf7fbf0e3ef13f80,0x3e953f7b3f22bec4,0x3f46be48bf75bf35,0xbf62bf553dc93f6d,
0x3f7c3eacbf27bf7b,0xbf1dbf7dbeb83f22,0xbf31bf78be893f35,0xbea13f2c3f7a3e95,0xbf09bf80bee63f0e,0xbefc3f043f803ef1,0xbecf3f183f7e3ec4,0x3f7f3edbbf13bf7f,
0xbe2fbf71bf423e48,0xbf4a3e163f6f3f46,0xbf393e793f773f35,0x3f733f3ebe60bf75,0xbf583d493f653f55,0x3f5f3f5cbcc9bf62,0x3f6a3f4ebdfbbf6d,0xbd97bf67bf513dc9,
0x3f2cbe95bf78bf35,0xbf7dbf223eac3f7b,0x3edb3f7f3f18bec4,0x3f04bef1bf80bf0e,0x3d493f623f5c0000,0x3f4ebdc9bf67bf55,0xbf71bf463e163f6d,0x3e793f753f3ebe48,
0xbf3ebf75be793f35,0xbe163f463f713e48,0x3f673dc9bf4ebf6d,0xbf5cbf62bd493f55,0x3f803ef1bf04bf80,0xbf18bf7fbedb3f0e,0xbeac3f223f7d3ec4,0x3f783e95bf2cbf7b,
0xbea1bf78bf393e48,0xbf093edb3f7e3f22,0xbf5fbd493f513f6d,0x3f6f3f4ebd97bf62,0x3f273f7d3ecfbf0e,0x3e2fbf3ebf77be95,0x3f1dbeacbf7abf35,0xbf80bf043ee63f7f,
0xbf73be793f313f7b,0x3f583f673dfbbf46,0x3efc3f803f13bec4,0x3eb8bf18bf7fbef1,0x3f42be16bf6abf55,0xbf7cbf2c3e893f75,0xbf4abf71be603f35,0x3cc93f5c3f653dc9,
0xbf7bbec43f0e3f80,0x3f553f6d3e48bf35,0xbe48bf6dbf550000,0xbf0e3ec43f7b3f35,0x3f7b3ec4bf0ebf80,0xbf55bf6dbe483f35,0x3e483f6d3f550000,0x3f0ebec4bf7bbf35,
0x3e483f6d3f558000,0x3f0ebec4bf7bbf35,0xbf7bbec43f0e3f80,0x3f553f6d3e48bf35,0xbe48bf6dbf558000,0xbf0e3ec43f7b3f35,0x3f7b3ec4bf0ebf80,0xbf55bf6dbe483f35,
0xbea13f183f803f0e,0x3f583d49bf4abf75,0x3f5f3f673e2fbf35,0xbeb8bf78bf423dc9,0xbd97bf5cbf6abe48,0xbf133eac3f773f46,0xbf7ebf2c3e603f6d,0x3f313f7d3ee6bef1,
0x3f733f4ebcc9bf55,0xbf09bf80bf1d3e95,0x3efcbedbbf7cbf35,0xbf6fbe793f273f7f,0xbf7fbf043ecf3f7b,0x3f513f713e89bf22,0xbdfb3f3e3f7a3ec4,0x3f39be16bf65bf62,
0x3f673f623e16bf35,0xbf04bf7fbf2c3e48,0xbd493f463f783ec4,0x3f18be95bf71bf55,0xbeacbf75bf4e0000,0xbe793f223f803f0e,0x3f3ebdc9bf5cbf6d,0xbf7dbef13edb3f7b,
0x3edbbef1bf7dbf35,0xbf5cbdc93f3e3f7b,0x3f803f22be79bf6d,0xbf4ebf75beac3f0e,0xbf71be953f183f80,0x3f783f46bd49bf55,0xbf2cbf7fbf043ec4,0x3e163f623f673e48,
0x3e2fbf2cbf7fbf0e,0xbf1d3e793f6a3f62,0xbf39bf7dbefc3ec4,0x3ea13f713f583dc9,0xbf7abedb3ee63f7b,0x3f773f4e3cc9bf46,0xbeb83f043f7e3f35,0x3f42bd49bf51bf75,
0xbf7cbf3e3d973f55,0x3f4a3f783ecfbef1,0xbf313e163f5f3f6d,0x3f733eacbf09bf7f,0x3e603f673f653e48,0x3e89bf18bf80bf22,0x3f6f3f5c3dfbbf35,0xbf27bf80bf133e95,
0x3f623e48bf22bf80,0xbf7fbf0e3e953f6d,0x3f753f553dc9bf35,0xbf46bf7bbef13ec4,0x3ef13f7b3f460000,0xbdc9bf55bf75bec4,0xbe953f0e3f7f3f35,0x3f22be48bf62bf6d,
0xbef1bf7bbf468000,0x3dc93f553f753ec4,0x3e95bf0ebf7fbf35,0xbf223e483f623f6d,0x3f623e48bf22bf80,0xbf7fbf0e3e953f6d,0x3f753f553dc9bf35,0xbf46bf7bbef13ec4,
0xbf31bf80bf1d3e48,0x3ee63f783f513dc9,0xbf7abf4ebd973f35,0x3f5f3f713eb8bef1,0x3ecfbedbbf77bf55,0xbf273e163f583f75,0xbe2fbf5cbf73bec4,0xbdfb3f2c3f803f22,
0xbf393d493f4a3f7b,0x3f653e79bf13bf7f,0xbe603f183f7f3f35,0x3efcbeacbf6fbf62,0xbf6abf67be893f0e,0x3f423f7d3f09be95,0xbf7cbf043ea13f6d,0x3f7e3f3ebcc9bf46,
0xbe163f223f803f35,0x3eacbef1bf78bf55,0xbf043e953f673f6d,0x3f2cbdc9bf4ebf7b,0x3f183f7f3f3e0000,0xbedbbf75bf5cbe48,0x3e793f623f713ec4,0xbd49bf46bf7dbf0e,
0x3f7d3f463d49bf35,0xbf71bf62be793f0e,0x3f5c3f753edbbec4,0xbf3ebf7fbf183e48,0x3f4e3dc9bf2cbf80,0xbf67be953f043f7b,0x3f783ef1beacbf6d,0xbf80bf223e163f55,
0x3f1dbe16bf51bf7b,0xbf313d493f423f7f,0x3ee6beacbf6abf6d,0xbf093e793f5f3f75,0x3e89bf04bf7abf55,0xbeb83edb3f733f62,0x3d97bf2cbf80bf35,0xbe2f3f183f7e3f46,
0xbf4abf7dbf133e48,0x3f393f803f27bdc9,0xbf65bf71becf3ec4,0x3f583f783efcbe95,0xbf77bf5cbe603f0e,0x3f6f3f673ea1bef1,0xbf7fbf3ebcc93f35,0x3f7c3f4e3dfbbf22,
0x3f003f003f003f00,0x3f003f003f003f00,0x3f003f003f003f00,0x3f003f003f003f00,0x3f003f003f003f00,0x3f003f003f003f00,0x3f003f003f003f00,0x3f003f003f003f00,
0xbf003f00bf003f00,0xbf003f00bf003f00,0xbf003f00bf003f00,0xbf003f00bf003f00,0xbf003f00bf003f00,0xbf003f00bf003f00,0xbf003f00bf003f00,0xbf003f00bf003f00,
0xbf77bf78bf7abf7b,0xbf6fbf71bf73bf75,0xbf7fbf80bf80bf80,0xbf7cbf7dbf7ebf7f,0xbf4abf4ebf51bf55,0xbf39bf3ebf42bf46,0xbf65bf67bf6abf6d,0xbf58bf5cbf5fbf62,
0x3e893e793e603e48,0x3eb83eac3ea13e95,0x3d973d493cc98000,0x3e2f3e163dfb3dc9,0x3f1d3f183f133f0e,0x3f313f2c3f273f22,0x3ee63edb3ecf3ec4,0x3f093f043efc3ef1,
0x3f183f223f2c3f35,0x3edb3ef13f043f0e,0x3e793e953eac3ec4,0x3d493dc93e163e48,0x3f7d3f7f3f803f80,0x3f713f753f783f7b,0x3f5c3f623f673f6d,0x3f3e3f463f4e3f55,
0xbf4ebf46bf3ebf35,0xbf67bf62bf5cbf55,0xbf78bf75bf71bf6d,0xbf80bf7fbf7dbf7b,0xbe16bdc9bd498000,0xbeacbe95be79be48,0xbf04bef1bedbbec4,0xbf2cbf22bf18bf0e,
0x3ecf3eac3e893e48,0x3f273f183f093ef1,0xbe2fbe79bea1bec4,0x3dfb3d49bcc9bdc9,0xbf31bf3ebf4abf55,0xbee6bf04bf13bf22,0xbf7abf7dbf7fbf80,0xbf5fbf67bf6fbf75,
0x3f6a3f713f773f7b,0x3f423f4e3f583f62,0x3f7c3f783f733f6d,0x3f7e3f803f803f7f,0x3f393f2c3f1d3f0e,0x3f653f5c3f513f46,0x3e603e163d978000,0x3efc3edb3eb83e95,
0x3f753f7b3f7f3f80,0x3f463f553f623f6d,0x3ef13f0e3f223f35,0x3dc93e483e953ec4,0xbe95be48bdc90000,0xbf22bf0ebef1bec4,0xbf62bf55bf46bf35,0xbf7fbf7bbf75bf6d,
0xbe95be48bdc98000,0xbf22bf0ebef1bec4,0xbf62bf55bf46bf35,0xbf7fbf7bbf75bf6d,0xbf75bf7bbf7fbf80,0xbf46bf55bf62bf6d,0xbef1bf0ebf22bf35,0xbdc9be48be95bec4,
0xbe60beacbee6bf0e,0x3e893e163cc9bdc9,0xbf6fbf78bf7ebf80,0xbf27bf3ebf51bf62,0x3f7c3f803f7f3f7b,0x3f4a3f5c3f6a3f75,0x3f313f183efc3ec4,0x3f733f673f583f46,
0x3f7a3f713f653f55,0x3f773f7d3f803f7f,0x3eb83e793dfb8000,0x3f423f2c3f133ef1,0xbe2fbd493d973e48,0xbf1dbf04becfbe95,0x3f393f4e3f5f3f6d,0x3ea13edb3f093f22,
0xbf71bf62bf4ebf35,0xbf78bf7fbf80bf7b,0xbf2cbf46bf5cbf6d,0xbe16be95bedbbf0e,0x3f673f753f7d3f80,0x3f043f223f3e3f55,0xbd493dc93e793ec4,0xbf18bef1beacbe48,
0xbeacbef1bf18bf35,0x3e793dc9bd49be48,0x3f3e3f223f043ec4,0x3f7d3f753f673f55,0xbedbbe95be168000,0xbf5cbf46bf2cbf0e,0xbf80bf7fbf78bf6d,0xbf4ebf62bf71bf7b,
0x3d973e793ecf3f0e,0xbf13bedbbe89bdc9,0x3f7e3f803f7a3f6d,0x3f313f4e3f653f75,0x3ea13e16bcc9be48,0x3f583f3e3f1d3ef1,0xbf5fbf71bf7cbf80,0xbeb8bf04bf27bf46,
0xbf7fbf78bf6abf55,0xbf51bf67bf77bf7f,0xbdfb3d493e603ec4,0xbf39bf18bee6be95,0x3f733f7d3f803f7b,0x3f093f2c3f4a3f62,0x3efc3eac3e2f8000,0x3f6f3f5c3f423f22,
0x3f553f6d3f7b3f80,0x3e483ec43f0e3f35,0xbf0ebec4be480000,0xbf7bbf6dbf55bf35,0xbf55bf6dbf7bbf80,0xbe48bec4bf0ebf35,0x3f0e3ec43e480000,0x3f7b3f6d3f553f35,
0xbf0ebec4be488000,0xbf7bbf6dbf55bf35,0xbf55bf6dbf7bbf80,0xbe48bec4bf0ebf35,0x3f0e3ec43e488000,0x3f7b3f6d3f553f35,0x3f553f6d3f7b3f80,0x3e483ec43f0e3f35,
0x3f423f183ecf3e48,0x3f7c3f803f773f62,0xbf4abf67bf7abf80,0xbcc9be79bee6bf22,0xbf73bf5cbf39bf0e,0xbf58bf71bf7ebf7f,0x3efc3f2c3f513f6d,0xbeb8be163d973e95,
0x3f273f4e3f6a3f7b,0xbe2f3d493e893ef1,0x3f1d3edb3e608000,0x3f803f783f653f46,0xbea1bf04bf31bf55,0x3f093eac3dfbbdc9,0xbf5fbf3ebf13bec4,0xbf6fbf7dbf7fbf75,
0xbd49be95bf04bf35,0x3f4e3f223edb3e48,0x3f713f7f3f7d3f6d,0x3e793ef13f2c3f55,0x3f3e3f623f783f80,0xbe163dc93eac3f0e,0xbf67bf46bf18bec4,0xbf5cbf75bf80bf7b,
0x3f803f753f5c3f35,0x3f183f463f673f7b,0xbeacbdc93e163ec4,0xbf78bf62bf3ebf0e,0xbf2cbef1be798000,0xbf7dbf7fbf71bf55,0xbedbbf22bf4ebf6d,0x3f043e953d49be48,
0xbf09bf3ebf65bf7b,0x3efc3e79bcc9be95,0xbecfbe163dfb3ec4,0xbf7fbf71bf51bf22,0x3f7c3f673f423f0e,0x3f1d3f4e3f6f3f7f,0xbf31bf5cbf77bf80,0x3ea13d49be60bef1,
0x3f583f2c3ee63e48,0x3f5f3f783f803f75,0xbf6abf7dbf7ebf6d,0xbd97beacbf13bf46,0x3e2f3edb3f273f55,0xbf4abf18beb8bdc9,0x3f393f043e898000,0x3f733f803f7a3f62,
0x3f223f553f753f80,0xbef1be483dc93ec4,0xbf7fbf7bbf62bf35,0xbe95bf0ebf46bf6d,0x3f463f0e3e950000,0x3f623f7b3f7f3f6d,0xbdc93e483ef13f35,0xbf75bf55bf22bec4,
0xbf46bf0ebe958000,0xbf62bf7bbf7fbf6d,0x3dc9be48bef1bf35,0x3f753f553f223ec4,0x3f223f553f753f80,0xbef1be483dc93ec4,0xbf7fbf7bbf62bf35,0xbe95bf0ebf46bf6d,
0x3f6f3f803f773f55,0xbd973e793f093f46,0xbf13bf4ebf73bf80,0x3f1d3eac3cc9be95,0x3f313edb3dfbbe48,0x3f653f7d3f7c3f62,0xbf7abf5cbf27bec4,0xbefcbf3ebf6abf7f,
0xbeb8bd493e893f0e,0xbf7fbf78bf58bf22,0x3f513f183ea18000,0x3f4a3f713f803f75,0x3f393f673f7e3f7b,0xbee6be163e2f3ef1,0xbe60bf04bf42bf6d,0x3f5f3f2c3ecf3dc9,
0x3f783f7f3f673f35,0xbd493e953f183f55,0xbf7dbf62bf2cbec4,0xbeacbf22bf5cbf7b,0x3f043f463f713f80,0xbf3ebef1be163e48,0xbf4ebf75bf80bf6d,0x3edb3dc9be79bf0e,
0xbe793dc93edb3f35,0xbf80bf75bf4ebf0e,0xbe16bef1bf3ebf6d,0x3f713f463f043e48,0xbf5cbf22beac8000,0xbf2cbf62bf7dbf7b,0x3f183e95bd49bec4,0x3f673f7f3f783f55,
0x3f5f3f7d3f7a3f55,0xbecfbd493ea13f22,0xbf42bf71bf80bf6d,0x3f133e79bdfbbef1,0x3f1d3f5c3f7c3f7b,0xbf39bedbbd973e95,0xbee6bf3ebf6fbf80,0x3f583f183e89bdc9,
0xbefcbe163e603f0e,0xbf6abf80bf73bf46,0x3f273eacbcc9bec4,0x3f513f783f7e3f62,0xbf4abf04be2f3e48,0xbf31bf67bf7fbf75,0x3f653f2c3eb88000,0x3f093f4e3f773f7f,
0x3ec43f353f6d3f80,0xbf6dbf35bec40000,0xbec4bf35bf6dbf80,0x3f6d3f353ec40000,0x3ec43f353f6d3f80,0xbf6dbf35bec40000,0xbec4bf35bf6dbf80,0x3f6d3f353ec40000,
0xbf6dbf35bec48000,0xbec4bf35bf6dbf80,0x3f6d3f353ec48000,0x3ec43f353f6d3f80,0xbf6dbf35bec48000,0xbec4bf35bf6dbf80,0x3f6d3f353ec48000,0x3ec43f353f6d3f80,
0x3dfb3f043f513f7b,0xbf80bf67bf27be95,0xbea1bf2cbf6abf80,0x3f7a3f4e3efc3dc9,0xbe893e163f093f55,0xbf6fbf80bf65bf22,0x3d97beacbf31bf6d,0x3f7c3f783f4a3ef1,
0xbf7ebf5cbf13be48,0xbcc9bedbbf42bf75,0x3f733f3e3ecf8000,0x3e603f183f5f3f7f,0xbf77bf7dbf58bf0e,0x3eb8bd49bee6bf46,0x3f7f3f713f393ec4,0xbe2f3e793f1d3f62,
0xbf04bdc93eac3f35,0xbf3ebf75bf7dbf55,0x3f4e3ef13d49bec4,0x3edb3f463f783f7b,0x3e793f223f673f80,0xbf80bf62bf18be48,0x3e16be95bf2cbf6d,0x3f713f7f3f5c3f0e,
0xbf5cbf7fbf71bf35,0x3f2c3e95be16bf0e,0x3f183f623f803f6d,0xbf67bf22be793e48,0xbf78bf46bedb8000,0xbd49bef1bf4ebf7b,0x3f7d3f753f3e3ec4,0xbeac3dc93f043f55,
0xbf80bf67bf1dbe48,0x3ea1be16bf13bf62,0x3f583f043d97bec4,0x3e893f2c3f6f3f7f,0xbecf3d493efc3f55,0xbf42bf78bf7abf46,0xbe2fbf18bf65bf80,0x3f7e3f713f313e95,
0x3cc9bedbbf4abf7b,0x3f733f7d3f513ef1,0x3f093f5c3f7f3f6d,0xbf77bf3ebeb83dc9,0xbf6abf80bf5fbf0e,0x3f273e79be60bf22,0x3f7c3f4e3ee68000,0xbdfb3eac3f393f75,
0x3dc93f0e3f623f80,0xbf75bf7bbf46bec4,0x3f223e48be95bf35,0x3ef13f553f7f3f6d,0xbf7fbf55bef10000,0x3e95be48bf22bf6d,0x3f463f7b3f753f35,0xbf62bf0ebdc93ec4,
0xbf7fbf55bef18000,0x3e95be48bf22bf6d,0x3f463f7b3f753f35,0xbf62bf0ebdc93ec4,0xbdc9bf0ebf62bf80,0x3f753f7b3f463ec4,0xbf22be483e953f35,0xbef1bf55bf7fbf6d,
0xbf51bedb3d973f0e,0xbdfbbf18bf6abf7f,0xbcc9bf04bf5fbf80,0x3f653f803f583ef1,0xbe60bf2cbf73bf7b,0x3f773f783f393e95,0x3f6f3f7d3f4a3ec4,0xbf42beac3e2f3f22,
0xbf13bf67bf7fbf55,0x3f7e3f4e3ecfbdc9,0x3f803f5c3efc8000,0xbee63d493f093f62,0x3f7a3f3e3ea1be48,0xbe893e793f313f75,0xbeb83e163f1d3f6d,0xbf27bf71bf7cbf46,
0xbf2cbf75bf78bf35,0x3f7d3f463eacbe48,0xbedb3dc93f183f6d,0xbf04bf62bf80bf55,0xbd493ef13f5c3f80,0xbf4ebf7fbf67bf0e,0x3f713f223e16bec4,0xbe793e953f3e3f7b,
0x3f3e3e95be79bf35,0x3e163f223f713f7b,0xbf67bf7fbf4ebec4,0x3f5c3ef1bd49bf0e,0xbf80bf62bf048000,0x3f183dc9bedbbf55,0x3eac3f463f7d3f6d,0xbf78bf75bf2cbe48,
0x3f653f04bcc9bf0e,0xbe603eac3f4a3f7f,0x3e893f3e3f7c3f6d,0xbf6abf7dbf42be95,0xbf7fbf4ebeb83e48,0x3f133d49befcbf62,0x3dfbbedbbf58bf80,0x3f313f783f733f22,
0x3ee63f5c3f803f55,0xbf7abf71bf1dbdc9,0xbf77bf2cbe2f3ec4,0x3ecfbe16bf27bf75,0xbd97bf18bf6fbf7b,0x3f513f803f5f3ef1,0x3f7e3f673f098000,0xbf39be793ea13f46,
0xbe483ec43f553f80,0xbf0ebf6dbf7bbf35,0x3f7b3f6d3f0e0000,0xbf55bec43e483f35,0x3e48bec4bf55bf80,0x3f0e3f6d3f7b3f35,0xbf7bbf6dbf0e0000,0x3f553ec4be48bf35,
0xbf7bbf6dbf0e8000,0x3f553ec4be48bf35,0xbe483ec43f553f80,0xbf0ebf6dbf7bbf35,0x3f7b3f6d3f0e8000,0xbf55bec43e483f35,0x3e48bec4bf55bf80,0x3f0e3f6d3f7b3f35,
0xbf65bf7dbf39be48,0x3f7a3f2c3dfbbef1,0x3e89beacbf51bf80,0x3ecf3f5c3f7f3f46,0x3f273f783f6f3f0e,0xbf7cbf67befc3dc9,0xbf1dbd493f093f6d,0xbcc9bf18bf73bf75,
0x3ee6be16bf31bf7b,0x3e603f3e3f7e3f62,0x3f773f713f138000,0xbf6abf043d973f22,0xbf42be793eb83f55,0x3e2fbedbbf5fbf7f,0xbf4abf80bf58bec4,0x3f803f4e3ea1be95,
0x3f673ef1be16bf35,0xbf043dc93f2c3f7b,0xbd49bf22bf78bf6d,0x3f183f753f713f0e,0xbeac3e953f4e3f80,0xbe79bf46bf80bf55,0x3f3e3f7f3f5c3ec4,0xbf7dbf62bedb3e48,
0x3edb3f623f7d3f35,0xbf5cbf7fbf3ebe48,0x3f803f463e79bec4,0xbf4ebe953eac3f55,0xbf71bf75bf188000,0x3f783f223d49bf0e,0xbf2cbdc93f043f6d,0x3e16bef1bf67bf7b,
0xbf133d493f273f7b,0x3dfbbf04bf6fbf75,0xbf80bf4ebe893ec4,0x3f653edbbe60bf46,0xbf09bf71bf73bf0e,0x3f5f3f7d3f313dc9,0x3ecfbe79bf4abf80,0x3d973f2c3f7c3f62,
0xbf51bf80bf42be48,0x3f7e3f5c3eb8be95,0x3cc9bf18bf77bf6d,0x3ee63f673f7a3f22,0x3f583eacbea1bf55,0xbefc3e163f393f7f,0x3f6a3f783f1d8000,0xbf7fbf3ebe2f3ef1,
0xbef13e483f463f80,0x3dc9bf0ebf75bf6d,0x3e953f553f7f3f35,0xbf22bf7bbf62bec4,0x3f623f7b3f220000,0xbf7fbf55be953ec4,0x3f753f0ebdc9bf35,0xbf46be483ef13f6d,
0xbf62bf7bbf228000,0x3f7f3f553e95bec4,0xbf75bf0e3dc93f35,0x3f463e48bef1bf6d,0xbef13e483f463f80,0x3dc9bf0ebf75bf6d,0x3e953f553f7f3f35,0xbf22bf7bbf62bec4,
0xbcc9bf2cbf7ebf55,0x3ea13f5c3f7c3f22,0x3f09be16bf42bf80,0xbe893edb3f6a3f75,0xbf6fbf71befc3e48,0x3f7f3f4e3e60bef1,0xbf13bf78bf65bec4,0x3f4a3f803f393dc9,
0x3f803f3e3dfbbf0e,0xbf73bf043e2f3f46,0x3f583f7d3f278000,0xbf77bf67becf3e95,0x3eb8beacbf5fbf7b,0xbd973f183f7a3f62,0x3f513e79bee6bf6d,0xbf1d3d493f313f7f,
0x3e163f463f803f35,0xbeacbf62bf78bf0e,0x3f043f753f673ec4,0xbf2cbf7fbf4ebe48,0xbf183dc93f3e3f80,0x3edbbe95bf5cbf7b,0xbe793ef13f713f6d,0x3d49bf22bf7dbf55,
0xbf7dbf223d493f35,0x3f713ef1be79bf55,0xbf5cbe953edb3f6d,0x3f3e3dc9bf18bf7b,0xbf4ebf7fbf2c8000,0x3f673f753f04be48,0xbf78bf62beac3ec4,0x3f803f463e16bf0e,
0x3dfbbf18bf7cbf55,0xbcc93f2c3f7f3f46,0x3ea1bedbbf6fbf6d,0xbe603f043f773f62,0x3efcbe79bf58bf7b,0xbecf3eac3f653f75,0x3f27bd49bf39bf80,0xbf133e163f4a3f7f,
0x3f7e3f4e3e2fbf0e,0xbf80bf3ebd973f22,0x3f733f673eb8bec4,0xbf7abf5cbe893ef1,0x3f5f3f783f09be48,0xbf6abf71bee63e95,0x3f423f803f318000,0xbf51bf7dbf1d3dc9,
0x3f003f003f003f00,0x3f003f003f003f00,0x3f003f003f003f00,0x3f003f003f003f00,0x3f003f003f003f00,0x3f003f003f003f00,0x3f003f003f003f00,0x3f003f003f003f00,
0xbf003f00bf003f00,0xbf003f00bf003f00,0xbf003f00bf003f00,0xbf003f00bf003f00,0xbf003f00bf003f00,0xbf003f00bf003f00,0xbf003f00bf003f00,0xbf003f00bf003f00,
0xbefcbf04bf09bf0e,0xbecfbedbbee6bef1,0xbf27bf2cbf31bf35,0xbf13bf18bf1dbf22,0xbdfbbe16be2fbe48,0xbcc9bd49bd97bdc9,0xbea1beacbeb8bec4,0xbe60be79be89be95,
0x3f5f3f5c3f583f55,0x3f6a3f673f653f62,0x3f423f3e3f393f35,0x3f513f4e3f4a3f46,0x3f7e3f7d3f7c3f7b,0x3f803f803f7f3f7f,0x3f733f713f6f3f6d,0x3f7a3f783f773f75,
0xbf4ebf46bf3ebf35,0xbf67bf62bf5cbf55,0xbf78bf75bf71bf6d,0xbf80bf7fbf7dbf7b,0xbe16bdc9bd490000,0xbeacbe95be79be48,0xbf04bef1bedbbec4,0xbf2cbf22bf18bf0e,
0xbf18bf22bf2cbf35,0xbedbbef1bf04bf0e,0xbe79be95beacbec4,0xbd49bdc9be16be48,0xbf7dbf7fbf80bf80,0xbf71bf75bf78bf7b,0xbf5cbf62bf67bf6d,0xbf3ebf46bf4ebf55,
0x3eb83edb3efc3f0e,0x3d973e163e603e95,0x3f513f5c3f653f6d,0x3f1d3f2c3f393f46,0x3f803f803f7e3f7b,0x3f733f783f7c3f7f,0x3f583f4e3f423f35,0x3f773f713f6a3f62,
0xbf6fbf67bf5fbf55,0xbf7fbf7dbf7abf75,0xbf13bf04bee6bec4,0xbf4abf3ebf31bf22,0xbcc93d493dfb3e48,0xbea1be79be2fbdc9,0x3f093f183f273f35,0x3e893eac3ecf3ef1,
0xbf75bf7bbf7fbf80,0xbf46bf55bf62bf6d,0xbef1bf0ebf22bf35,0xbdc9be48be95bec4,0x3e953e483dc90000,0x3f223f0e3ef13ec4,0x3f623f553f463f35,0x3f7f3f7b3f753f6d,
0x3e953e483dc98000,0x3f223f0e3ef13ec4,0x3f623f553f463f35,0x3f7f3f7b3f753f6d,0x3f753f7b3f7f3f80,0x3f463f553f623f6d,0x3ef13f0e3f223f35,0x3dc93e483e953ec4,
0xbf09bedbbea1be48,0xbf5fbf4ebf39bf22,0x3ecf3f043f1d3f35,0xbd973d493e2f3e95,0xbf13bf2cbf42bf55,0xbdfbbe79beb8bef1,0xbf80bf7dbf77bf6d,0xbf65bf71bf7abf7f,
0xbf58bf67bf73bf7b,0xbefcbf18bf31bf46,0xbf6abf5cbf4abf35,0xbf7fbf80bf7cbf75,0x3f513f3e3f273f0e,0x3f7e3f783f6f3f62,0xbcc9be16be89bec4,0x3ee63eac3e603dc9,
0x3eac3ef13f183f35,0xbe79bdc93d493e48,0xbf3ebf22bf04bec4,0xbf7dbf75bf67bf55,0x3edb3e953e160000,0x3f5c3f463f2c3f0e,0x3f803f7f3f783f6d,0x3f4e3f623f713f7b,
0xbf71bf62bf4ebf35,0xbf78bf7fbf80bf7b,0xbf2cbf46bf5cbf6d,0xbe16be95bedbbf0e,0x3f673f753f7d3f80,0x3f043f223f3e3f55,0xbd493dc93e793ec4,0xbf18bef1beacbe48,
0x3f423f5c3f6f3f7b,0x3e2f3eac3efc3f22,0x3f4a3f2c3f093ec4,0x3f803f7d3f733f62,0xbee6bf18bf39bf55,0x3e603d49bdfbbe95,0xbf77bf67bf51bf35,0xbf6abf78bf7fbf7f,
0xbf27bf04beb8be48,0xbf7cbf71bf5fbf46,0x3f1d3f3e3f583f6d,0xbcc93e163ea13ef1,0x3f653f4e3f313f0e,0x3f7a3f803f7e3f75,0xbe89bedbbf13bf35,0x3ecf3e793d97bdc9,
0x3f553f6d3f7b3f80,0x3e483ec43f0e3f35,0xbf0ebec4be480000,0xbf7bbf6dbf55bf35,0xbf55bf6dbf7bbf80,0xbe48bec4bf0ebf35,0x3f0e3ec43e480000,0x3f7b3f6d3f553f35,
0xbf0ebec4be488000,0xbf7bbf6dbf55bf35,0xbf55bf6dbf7bbf80,0xbe48bec4bf0ebf35,0x3f0e3ec43e488000,0x3f7b3f6d3f553f35,0x3f553f6d3f7b3f80,0x3e483ec43f0e3f35,
0x3f7f3f7d3f6f3f55,0x3f133f3e3f5f3f75,0xbdfbbeacbf09bf35,0x3f313f043ea13dc9,0xbf65bf78bf80bf7b,0xbe60bedbbf1dbf46,0xbe89bd493e2f3ec4,0xbf6abf4ebf27bef1,
0xbd973e163eb83f0e,0xbf51bf2cbefcbe95,0x3f7e3f713f583f35,0x3f393f5c3f733f7f,0x3ee63e793cc9be48,0x3f7a3f673f4a3f22,0xbf77bf80bf7cbf6d,0xbecfbf18bf42bf62,
0x3f803f753f5c3f35,0x3f183f463f673f7b,0xbeacbdc93e163ec4,0xbf78bf62bf3ebf0e,0xbf2cbef1be790000,0xbf7dbf7fbf71bf55,0xbedbbf22bf4ebf6d,0x3f043e953d49be48,
0x3d493e953f043f35,0xbf4ebf22bedbbe48,0xbf71bf7fbf7dbf6d,0xbe79bef1bf2cbf55,0xbf3ebf62bf78bf80,0x3e16bdc9beacbf0e,0x3f673f463f183ec4,0x3f5c3f753f803f7b,
0x3f7a3f803f733f55,0x3e893f043f393f62,0xbeb8bf18bf4abf6d,0x3f273edb3e2fbdc9,0xbf13beacbd973e48,0xbf7ebf7dbf6abf46,0x3f803f783f5f3f35,0x3ee63f2c3f583f75,
0xbe603d493ea13f0e,0xbf77bf5cbf31bef1,0x3f6f3f4e3f1d3ec4,0x3f423f673f7c3f7f,0xbf51bf71bf7fbf7b,0x3dfbbe16becfbf22,0xbcc93e793efc3f35,0xbf65bf3ebf09be95,
0xbf22bf55bf75bf80,0x3ef13e48bdc9bec4,0x3f7f3f7b3f623f35,0x3e953f0e3f463f6d,0xbf46bf0ebe950000,0xbf62bf7bbf7fbf6d,0x3dc9be48bef1bf35,0x3f753f553f223ec4,
0x3f463f0e3e958000,0x3f623f7b3f7f3f6d,0xbdc93e483ef13f35,0xbf75bf55bf22bec4,0xbf22bf55bf75bf80,0x3ef13e48bdc9bec4,0x3f7f3f7b3f623f35,0x3e953f0e3f463f6d,
0xbecfbf2cbf5fbf7b,0x3f423f043e60bdc9,0xbe2f3e163ee63f35,0xbf7ebf67bf39bef1,0xbf80bf71bf4abf0e,0xbea1bf18bf51bf75,0x3f583f783f7f3f6d,0xbe893d493eb83f22,
0x3f6a3f3e3efc3e48,0x3f273f5c3f7a3f7f,0xbf7cbf7dbf65bf35,0xbdfbbedbbf31bf62,0xbcc9beacbf1dbf55,0x3f733f4e3f133e95,0xbf09be793d973ec4,0xbf77bf80bf6fbf46,
0x3e79bdc9bedbbf35,0x3f803f753f4e3f0e,0x3e163ef13f3e3f6d,0xbf71bf46bf04be48,0x3f5c3f223eac0000,0x3f2c3f623f7d3f7b,0xbf18be953d493ec4,0xbf67bf7fbf78bf55,
0x3f783f7f3f673f35,0xbd493e953f183f55,0xbf7dbf62bf2cbec4,0xbeacbf22bf5cbf7b,0x3f043f463f713f80,0xbf3ebef1be163e48,0xbf4ebf75bf80bf6d,0x3edb3dc9be79bf0e,
0x3f773f4e3f093e48,0x3eb83f2c3f653f7f,0xbf7fbf67bf31bec4,0xbe2fbf04bf4abf75,0x3f7e3f783f513f0e,0xbcc93eac3f273f62,0xbf73bf80bf6abf35,0x3e60be16befcbf46,
0x3e893f183f583f7b,0xbf6fbf3ebee6bdc9,0xbd97bedbbf39bf6d,0x3f7c3f5c3f1d3e95,0xbdfb3e793f133f55,0xbf80bf71bf42bef1,0x3ea1bd49becfbf35,0x3f7a3f7d3f5f3f22,
0x3ec43f353f6d3f80,0xbf6dbf35bec40000,0xbec4bf35bf6dbf80,0x3f6d3f353ec40000,0x3ec43f353f6d3f80,0xbf6dbf35bec40000,0xbec4bf35bf6dbf80,0x3f6d3f353ec40000,
0xbf6dbf35bec48000,0xbec4bf35bf6dbf80,0x3f6d3f353ec48000,0x3ec43f353f6d3f80,0xbf6dbf35bec48000,0xbec4bf35bf6dbf80,0x3f6d3f353ec48000,0x3ec43f353f6d3f80,
0xbf1dbe793e2f3f0e,0xbf39bf71bf7fbf62,0x3ee63d49beb8bf35,0x3f583f7d3f773f46,0xbf5fbf18be603e48,0xbecfbf3ebf73bf7f,0x3f423edb3cc9bec4,0x3f133f5c3f7e3f75,
0xbf4abf78bf7cbf55,0x3f313eacbd97bef1,0x3f653f803f6f3f35,0xbf09be163e893f22,0xbefcbf4ebf7abf7b,0x3f6a3f2c3ea1bdc9,0x3f273f673f803f6d,0xbf51bf04bdfb3e95,
0xbf5cbf7fbf71bf35,0x3f2c3e95be16bf0e,0x3f183f623f803f6d,0xbf67bf22be793e48,0xbf78bf46bedb0000,0xbd49bef1bf4ebf7b,0x3f7d3f753f3e3ec4,0xbeac3dc93f043f55,
0x3f043dc9beacbf35,0x3f3e3f753f7d3f55,0xbf4ebef1bd493ec4,0xbedbbf46bf78bf7b,0xbe79bf22bf67bf80,0x3f803f623f183e48,0xbe163e953f2c3f6d,0xbf71bf7fbf5cbf0e,
0x3f393eacbdfbbf0e,0x3ee63f4e3f7c3f75,0xbe603e793f273f6d,0xbf5fbf80bf6abf22,0xbeb8bf3ebf77bf7b,0x3f7f3f5c3f093dc9,0x3f513f7d3f733f35,0xbf4abedb3cc93ef1,
0x3f313f713f7e3f55,0xbf65bf18be2f3e95,0xbf7abf78bf42bec4,0x3efc3d49becfbf46,0x3f6f3f2c3e89be48,0x3d973f043f583f7f,0xbf13be163ea13f35,0xbf1dbf67bf80bf62,
0xbdc9bf0ebf62bf80,0x3f753f7b3f463ec4,0xbf22be483e953f35,0xbef1bf55bf7fbf6d,0x3f7f3f553ef10000,0xbe953e483f223f6d,0xbf46bf7bbf75bf35,0x3f623f0e3dc9bec4,
0x3f7f3f553ef18000,0xbe953e483f223f6d,0xbf46bf7bbf75bf35,0x3f623f0e3dc9bec4,0x3dc93f0e3f623f80,0xbf75bf7bbf46bec4,0x3f223e48be95bf35,0x3ef13f553f7f3f6d,
0x3f7c3f713f273e48,0xbf1dbe163eb83f46,0xbf31be793e893f35,0xbea1bf3ebf7abf75,0xbf09bd493ee63f55,0xbefcbf5cbf80bf62,0xbecfbf4ebf7ebf6d,0x3f7f3f673f133dc9,
0xbe2f3eac3f423f7b,0xbf4abf7dbf6fbf22,0xbf39bf78bf77bf35,0x3f733f2c3e60be95,0xbf58bf80bf65bf0e,0x3f5f3f043cc9bef1,0x3f6a3f183dfbbec4,0xbd973edb3f513f7f,
0xbf3ebe953e793f35,0xbe16bf22bf71bf7b,0x3f673f7f3f4e3ec4,0xbf5cbef13d493f0e,0x3f803f623f040000,0xbf18bdc93edb3f55,0xbeacbf46bf7dbf6d,0x3f783f753f2c3e48,
0xbf2cbf75bf78bf35,0x3f7d3f463eacbe48,0xbedb3dc93f183f6d,0xbf04bf62bf80bf55,0xbd493ef13f5c3f80,0xbf4ebf7fbf67bf0e,0x3f713f223e16bec4,0xbe793e953f3e3f7b,
0x3ea1be79bf39bf7b,0x3f093f673f7e3f46,0x3f5f3f803f513ec4,0xbf6fbf18bd973ef1,0xbf27be163ecf3f55,0xbe2fbf2cbf77bf75,0xbf1dbf71bf7abf35,0x3f803f5c3ee6bdc9,
0x3f733f783f313e48,0xbf58bedb3dfb3f22,0xbefc3d493f133f6d,0xbeb8bf4ebf7fbf62,0xbf42bf7dbf6abf0e,0x3f7c3f3e3e89be95,0x3f4a3eacbe60bf35,0xbcc93f043f653f7f,
0xbe483ec43f553f80,0xbf0ebf6dbf7bbf35,0x3f7b3f6d3f0e0000,0xbf55bec43e483f35,0x3e48bec4bf55bf80,0x3f0e3f6d3f7b3f35,0xbf7bbf6dbf0e0000,0x3f553ec4be48bf35,
0xbf7bbf6dbf0e8000,0x3f553ec4be48bf35,0xbe483ec43f553f80,0xbf0ebf6dbf7bbf35,0x3f7b3f6d3f0e8000,0xbf55bec43e483f35,0x3e48bec4bf55bf80,0x3f0e3f6d3f7b3f35,
0xbea1bf4ebf80bf55,0x3f583f803f4a3e95,0x3f5f3edbbe2fbf35,0xbeb83e793f423f7f,0xbd973f043f6a3f7b,0xbf13bf71bf77bf22,0xbf7ebf3ebe603ec4,0x3f313e16bee6bf62,
0x3f733f183cc9bf0e,0xbf093d493f1d3f75,0x3efc3f673f7c3f35,0xbf6fbf78bf27bdc9,0xbf7fbf5cbecf3e48,0x3f513eacbe89bf46,0xbdfbbf2cbf7abf6d,0x3f393f7d3f653ef1,
0x3edb3f623f7d3f35,0xbf5cbf7fbf3ebe48,0x3f803f463e79bec4,0xbf4ebe953eac3f55,0xbf71bf75bf180000,0x3f783f223d49bf0e,0xbf2cbdc93f043f6d,0x3e16bef1bf67bf7b,
0xbf67bef13e163f35,0x3f04bdc9bf2cbf7b,0x3d493f223f783f6d,0xbf18bf75bf71bf0e,0x3eacbe95bf4ebf80,0x3e793f463f803f55,0xbf3ebf7fbf5cbec4,0x3f7d3f623edbbe48,
0xbe2fbf3ebf7fbf55,0x3f1d3f783f6a3ef1,0x3f393e16befcbf6d,0xbea13eac3f583f7f,0x3f7a3f673ee6be48,0xbf77bf183cc93f22,0x3eb83f5c3f7e3f35,0xbf42bf80bf51be95,
0x3f7c3f2c3d97bf0e,0xbf4abe793ecf3f62,0x3f313f7d3f5f3ec4,0xbf73bf71bf093dc9,0xbe603edb3f653f7b,0xbe89bf4ebf80bf46,0xbf6fbf043dfb3f35,0x3f273d49bf13bf75,
0x3ef1be48bf46bf80,0xbdc93f0e3f753f6d,0xbe95bf55bf7fbf35,0x3f223f7b3f623ec4,0xbf62bf7bbf220000,0x3f7f3f553e95bec4,0xbf75bf0e3dc93f35,0x3f463e48bef1bf6d,
0x3f623f7b3f228000,0xbf7fbf55be953ec4,0x3f753f0ebdc9bf35,0xbf46be483ef13f6d,0x3ef1be48bf46bf80,0xbdc93f0e3f753f6d,0xbe95bf55bf7fbf35,0x3f223f7b3f623ec4,
0xbf31bd493f1d3f7b,0x3ee6be79bf51bf7f,0xbf7abf183d973f35,0x3f5f3eacbeb8bf62,0x3ecf3f673f773f0e,0xbf27bf7dbf58be95,0xbe2f3f043f733f6d,0xbdfbbf3ebf80bf46,
0xbf39bf80bf4abe48,0x3f653f783f13bdc9,0xbe60bf4ebf7fbf35,0x3efc3f713f6f3ef1,0xbf6abedb3e893f55,0x3f423e16bf09bf75,0xbf7cbf5cbea13ec4,0x3f7e3f2c3cc9bf22,
0x3f7d3f22bd49bf35,0xbf71bef13e793f55,0x3f5c3e95bedbbf6d,0xbf3ebdc93f183f7b,0x3f4e3f7f3f2c0000,0xbf67bf75bf043e48,0x3f783f623eacbec4,0xbf80bf46be163f0e,
0x3e163f463f803f35,0xbeacbf62bf78bf0e,0x3f043f753f673ec4,0xbf2cbf7fbf4ebe48,0xbf183dc93f3e3f80,0x3edbbe95bf5cbf7b,0xbe793ef13f713f6d,0x3d49bf22bf7dbf55,
0xbf1dbf7dbf51be48,0x3f313f803f423dc9,0xbee6bf71bf6abec4,0x3f093f783f5f3e95,0xbe89bf5cbf7abf0e,0x3eb83f673f733ef1,0xbd97bf3ebf80bf35,0x3e2f3f4e3f7e3f22,
0x3f4a3e16bf13bf7b,0xbf39bd493f273f7f,0x3f653eacbecfbf6d,0xbf58be793efc3f75,0x3f773f04be60bf55,0xbf6fbedb3ea13f62,0x3f7f3f2cbcc9bf35,0xbf7cbf183dfb3f46,
0xbf8000003f80,0xbf8000003f80,0xbf8000003f80,0xbf8000003f80,0xbf8000003f80,0xbf8000003f80,0xbf8000003f80,0xbf8000003f80,
0x3f808000bf808000,0x3f808000bf808000,0x3f808000bf808000,0x3f808000bf808000,0x3f808000bf808000,0x3f808000bf808000,0x3f808000bf808000,0x3f808000bf808000,
0xbe893f783e60bf7b,0xbeb83f713ea1bf75,0xbd973f803cc9bf80,0xbe2f3f7d3dfbbf7f,0xbf1d3f4e3f13bf55,0xbf313f3e3f27bf46,0xbee63f673ecfbf6d,0xbf093f5c3efcbf62,
0xbf77be793f7a3e48,0xbf6fbeac3f733e95,0xbf7fbd493f808000,0xbf7cbe163f7e3dc9,0xbf4abf183f513f0e,0xbf39bf2c3f423f22,0xbf65bedb3f6a3ec4,0xbf58bf043f5f3ef1,
0x3f4ebf22bf3e3f35,0x3f67bef1bf5c3f0e,0x3f78be95bf713ec4,0x3f80bdc9bf7d3e48,0x3e16bf7fbd493f80,0x3eacbf75be793f7b,0x3f04bf62bedb3f6d,0x3f2cbf46bf183f55,
0x3f183f46bf2cbf35,0x3edb3f62bf04bf55,0x3e793f75beacbf6d,0x3d493f7fbe16bf7b,0x3f7d3dc9bf808000,0x3f713e95bf78be48,0x3f5c3ef1bf67bec4,0x3f3e3f22bf4ebf0e,
0xbf6abeac3f773e48,0xbf42bf183f583ef1,0xbf7c3e793f73bec4,0xbf7ebd493f80bdc9,0xbf393f3e3f1dbf55,0xbf653f043f51bf22,0xbe603f7d3d97bf80,0xbefc3f673eb8bf75,
0x3ecfbf71be893f7b,0x3f27bf4ebf093f62,0xbe2fbf783ea13f6d,0x3dfbbf803cc93f7f,0xbf31bf2c3f4a3f0e,0xbee6bf5c3f133f46,0xbf7abe163f7f8000,0xbf5fbedb3f6f3e95,
0x3e95bf7bbdc93f80,0x3f22bf55bef13f6d,0x3f62bf0ebf463f35,0x3f7fbe48bf753ec4,0x3f753e48bf7f0000,0x3f463f0ebf62bec4,0x3ef13f55bf22bf35,0x3dc93f7bbe95bf6d,
0x3f753e48bf7f8000,0x3f463f0ebf62bec4,0x3ef13f55bf22bf35,0x3dc93f7bbe95bf6d,0xbe953f7b3dc9bf80,0xbf223f553ef1bf6d,0xbf623f0e3f46bf35,0xbf7f3e483f75bec4,
0xbf7a3eac3f65bf0e,0xbf77be163f80bdc9,0xbeb83f783dfbbf80,0xbf423f3e3f13bf62,0x3e2fbf803d973f7b,0x3f1dbf5cbecf3f75,0xbf39bf183f5f3ec4,0xbea1bf673f093f46,
0xbe60bf713ee63f55,0x3e89bf7dbcc93f7f,0xbf6fbe793f7e8000,0xbf27bf2c3f513ef1,0x3f7c3d49bf7f3e48,0x3f4a3f04bf6abe95,0x3f31bf4ebefc3f6d,0x3f73bedbbf583f22,
0x3eac3f62bf18bf35,0xbe793f7fbd49bf7b,0xbf3e3f463f04bf6d,0xbf7d3e953f67bf0e,0x3edbbf75be163f80,0x3f5cbf22bf2c3f55,0x3f80bdc9bf783ec4,0x3f4e3ef1bf71be48,
0xbf713ef13f4ebf35,0xbf78bdc93f80be48,0xbf2cbf223f5c3ec4,0xbe16bf753edb3f55,0x3f673e95bf7d8000,0x3f043f46bf3ebf0e,0xbd493f7fbe79bf6d,0xbf183f623eacbf7b,
0x3f7fbe79bf6a3f0e,0x3f513edbbf77bdc9,0x3dfbbf803e603f6d,0x3f39bf4ebee63f75,0xbf73be163f80be48,0xbf09bf3e3f4a3ef1,0xbefc3f713e2fbf80,0xbf6f3f043f42bf46,
0x3d973f78becfbf55,0xbf133f673e89bf7f,0x3f7ebd49bf7a3ec4,0x3f313f18bf65be95,0x3ea1bf7d3cc93f7b,0x3f58bf2cbf1d3f62,0xbf5fbeac3f7c8000,0xbeb8bf5c3f273f22,
0x3f0ebf6dbe483f80,0x3f7bbec4bf553f35,0x3f553ec4bf7b0000,0x3e483f6dbf0ebf35,0xbf0e3f6d3e48bf80,0xbf7b3ec43f55bf35,0xbf55bec43f7b0000,0xbe48bf6d3f0e3f35,
0x3f553ec4bf7b8000,0x3e483f6dbf0ebf35,0xbf0e3f6d3e48bf80,0xbf7b3ec43f55bf35,0xbf55bec43f7b8000,0xbe48bf6d3f0e3f35,0x3f0ebf6dbe483f80,0x3f7bbec4bf553f35,
0xbf27bf183f6a3e48,0x3e2fbf803e893f62,0xbf1d3f673e60bf80,0xbf803e793f65bf22,0x3ea13f5cbf31bf0e,0xbf093f713dfbbf7f,0x3f5fbf2cbf133f6d,0x3f6f3e16bf7f3e95,
0x3f42bf4ebecf3f7b,0x3f7cbd49bf773ef1,0xbf4abedb3f7a8000,0xbcc9bf783ee63f46,0xbf733f043f39bf55,0xbf58beac3f7ebdc9,0x3efc3f3ebf51bec4,0xbeb83f7dbd97bf75,
0xbf803e953f5cbf35,0xbf18bf223f673e48,0x3eacbf7f3e163f6d,0x3f78bef1bf3e3f55,0x3f2cbf62be793f80,0x3f7dbdc9bf713f0e,0x3edb3f46bf4ebec4,0xbf043f753d49bf7b,
0xbd49bf753f043f35,0x3f4ebf46bedb3f7b,0x3f713dc9bf7d3ec4,0x3e793f62bf2cbf0e,0x3f3e3ef1bf788000,0xbe163f7fbeacbf55,0xbf673f223f18bf6d,0xbf5cbe953f80be48,
0xbf583f3e3ee6bf7b,0xbf5fbe793f80be95,0x3f6a3e16bf7e3ec4,0x3d973f71bf13bf22,0xbe2fbf673f273f0e,0x3f4abf4ebeb83f7f,0xbf393f5c3e89bf80,0xbf73bd493f7abef1,
0xbf09bf2c3f653e48,0x3efcbf783cc93f75,0xbecf3f7dbdfbbf6d,0xbf7f3eac3f51bf46,0x3f7cbedbbf423f55,0x3f1d3f18bf6fbdc9,0xbf31bf043f778000,0x3ea1bf803e603f62,
0x3f46bf55be953f80,0x3f623e48bf7f3ec4,0xbdc93f7bbef1bf35,0xbf753f0e3f22bf6d,0xbf22bf0e3f750000,0x3ef1bf7b3dc93f6d,0x3f7fbe48bf623f35,0x3e953f55bf46bec4,
0x3f223f0ebf758000,0xbef13f7bbdc9bf6d,0xbf7f3e483f62bf35,0xbe95bf553f463ec4,0x3f46bf55be953f80,0x3f623e48bf7f3ec4,0xbdc93f7bbef1bf35,0xbf753f0e3f22bf6d,
0x3eb8bf803e893f55,0x3f7fbe79bf583f46,0xbf513f4e3ea1bf80,0xbf4abeac3f80be95,0xbf39bedb3f7ebe48,0x3ee6bf7d3e2f3f62,0x3e603f5cbf42bec4,0xbf5f3f3e3ecfbf7f,
0x3f6f3d49bf773f0e,0xbd973f78bf09bf22,0xbf13bf183f738000,0x3f1dbf71bcc93f75,0x3f31bf67bdfb3f7b,0x3f653e16bf7c3ef1,0xbf7a3f043f27bf6d,0xbefcbf2c3f6a3dc9,
0x3e79bf7f3edb3f35,0x3f80be95bf4e3f55,0x3e163f62bf3ebec4,0xbf713f223f04bf7b,0x3f5cbf46beac3f80,0x3f2c3ef1bf7d3e48,0xbf183f75bd49bf6d,0xbf67bdc93f78bf0e,
0x3f78bdc9bf673f35,0xbd493f75bf18bf0e,0xbf7d3ef13f2cbf6d,0xbeacbf463f5c3e48,0x3f043f22bf718000,0xbf3e3f623e16bf7b,0xbf4ebe953f80bec4,0x3edbbf7f3e793f55,
0x3efcbf7d3e603f55,0x3f6a3d49bf733f22,0xbf273f71bcc9bf6d,0xbf51be793f7ebef1,0x3f4abf5cbe2f3f7b,0x3f313edbbf7f3e95,0xbf653f3e3eb8bf80,0xbf09bf183f77bdc9,
0x3f5f3e16bf7a3f0e,0xbecf3f80bea1bf46,0xbf42beac3f80bec4,0x3f13bf783dfb3f62,0x3f1d3f04bf7c3e48,0xbf393f673d97bf75,0xbee6bf2c3f6f8000,0x3f58bf4ebe893f7f,
0x3f6dbf35bec43f80,0x3ec43f35bf6d0000,0xbf6d3f353ec4bf80,0xbec4bf353f6d0000,0x3f6dbf35bec43f80,0x3ec43f35bf6d0000,0xbf6d3f353ec4bf80,0xbec4bf353f6d0000,
0x3ec43f35bf6d8000,0xbf6d3f353ec4bf80,0xbec4bf353f6d8000,0x3f6dbf35bec43f80,0x3ec43f35bf6d8000,0xbf6d3f353ec4bf80,0xbec4bf353f6d8000,0x3f6dbf35bec43f80,
0x3f7ebf04bf133f7b,0x3cc93f67bf42be95,0xbf733f2c3ecfbf80,0xbe60bf4e3f5f3dc9,0x3f77be16bf583f55,0xbeb83f80bee6bf22,0xbf7f3eac3f39bf6d,0x3e2fbf783f1d3ef1,
0x3dfb3f5cbf51be48,0xbf803edb3f27bf75,0xbea1bf3e3f6a8000,0x3f7abf18befc3f7f,0xbe893f7dbf09bf0e,0xbf6f3d493f65bf46,0x3d97bf713f313ec4,0x3f7cbe79bf4a3f62,
0x3f5c3dc9bf713f35,0xbf2c3f75be16bf55,0xbf18bef13f80bec4,0x3f67bf46be793f7b,0x3f78bf22bedb3f80,0x3d493f62bf4ebe48,0xbf7d3e953f3ebf6d,0x3eacbf7f3f043f0e,
0xbf043f7fbeacbf35,0xbf3ebe953f7dbf0e,0x3f4ebf62bd493f6d,0x3edb3f22bf783e48,0x3e793f46bf678000,0xbf803ef13f18bf7b,0x3e16bf753f2c3ec4,0x3f71bdc9bf5c3f55,
0xbcc93f67bf4abe48,0xbf733e163f51bf62,0xbf09bf043f7fbec4,0x3f77bf2cbeb83f7f,0x3f6abd49bf5f3f55,0xbf273f78be60bf46,0xbf7c3f183ee6bf80,0x3dfbbf713f393e95,
0xbf803edb3f1dbf7b,0x3ea1bf7d3f133ef1,0x3f58bf5cbd973f6d,0x3e893f3ebf6f3dc9,0xbecf3f80befcbf0e,0xbf42be793f7abf22,0xbe2fbf4e3f658000,0x3f7ebeacbf313f75,
0x3f7fbf0ebef13f80,0xbe953f7bbf22bec4,0xbf46be483f75bf35,0x3f62bf55bdc93f6d,0x3dc93f55bf620000,0xbf753e483f46bf6d,0x3f22bf7b3e953f35,0x3ef13f0ebf7f3ec4,
0x3dc93f55bf628000,0xbf753e483f46bf6d,0x3f22bf7b3e953f35,0x3ef13f0ebf7f3ec4,0xbf7f3f0e3ef1bf80,0x3e95bf7b3f223ec4,0x3f463e48bf753f35,0xbf623f553dc9bf6d,
0x3f133edbbf7f3f0e,0xbf7e3f183ecfbf7f,0xbf803f043efcbf80,0x3ee6bf803f093ef1,0xbf7a3f2c3ea1bf7b,0x3e89bf783f313e95,0x3eb8bf7d3f1d3ec4,0x3f273eacbf7c3f22,
0xbf513f67bd97bf55,0xbdfbbf4e3f6abdc9,0xbcc9bf5c3f5f8000,0x3f65bd49bf583f62,0xbe60bf3e3f73be48,0x3f77be79bf393f75,0x3f6fbe16bf4a3f6d,0xbf423f71be2fbf46,
0xbf3e3f75be79bf35,0xbe16bf463f71be48,0x3f67bdc9bf4e3f6d,0xbf5c3f62bd49bf55,0x3f80bef1bf043f80,0xbf183f7fbedbbf0e,0xbeacbf223f7dbec4,0x3f78be95bf2c3f7b,
0xbf2cbe953f78bf35,0x3f7dbf22beac3f7b,0xbedb3f7fbf18bec4,0xbf04bef13f80bf0e,0xbd493f62bf5c8000,0xbf4ebdc93f67bf55,0x3f71bf46be163f6d,0xbe793f75bf3ebe48,
0xbee6bf043f80bf0e,0x3f7abeacbf1d3f7f,0x3f77bf3ebe2f3f6d,0xbecf3f7dbf27be95,0x3d973f4ebf6f3e48,0xbf51bd493f5fbf62,0xbf7e3edb3f09bf80,0x3f39bf783ea13f22,
0x3f65bf5c3cc93f55,0xbe603f71bf4abdc9,0x3e893f2cbf7c3ec4,0xbf6a3e163f42bf75,0xbf7f3f183eb8bf7b,0x3f13bf803efc3ef1,0x3dfbbf673f588000,0x3f313e79bf733f46,
0x3f7bbec4bf0e3f80,0xbf553f6dbe48bf35,0x3e48bf6d3f550000,0x3f0e3ec4bf7b3f35,0xbf7b3ec43f0ebf80,0x3f55bf6d3e483f35,0xbe483f6dbf550000,0xbf0ebec43f7bbf35,
0xbe483f6dbf558000,0xbf0ebec43f7bbf35,0x3f7bbec4bf0e3f80,0xbf553f6dbe48bf35,0x3e48bf6d3f558000,0x3f0e3ec4bf7b3f35,0xbf7b3ec43f0ebf80,0x3f55bf6d3e483f35,
0xbee63f7dbf31be48,0xbe60bf2c3f7ebef1,0xbf773eac3f13bf80,0x3f6abf5c3d973f46,0x3f42bf783eb83f0e,0xbe2f3f67bf5f3dc9,0x3f4a3d49bf583f6d,0xbf803f183ea1bf75,
0xbf653e163f39bf7b,0x3f7abf3ebdfb3f62,0x3e89bf713f518000,0x3ecf3f04bf7f3f22,0x3f273e79bf6f3f55,0xbf7c3edb3efcbf7f,0xbf1d3f80bf09bec4,0xbcc9bf4e3f73be95,
0xbedbbef13f7dbf35,0x3f5cbdc9bf3e3f7b,0xbf803f223e79bf6d,0x3f4ebf753eac3f0e,0x3f71be95bf183f80,0xbf783f463d49bf55,0x3f2cbf7f3f043ec4,0xbe163f62bf673e48,
0x3f67bf623e163f35,0xbf043f7fbf2cbe48,0xbd49bf463f78bec4,0x3f183e95bf713f55,0xbeac3f75bf4e8000,0xbe79bf223f80bf0e,0x3f3e3dc9bf5c3f6d,0xbf7d3ef13edbbf7b,
0x3f51bd49bf423f7b,0xbf7e3f043eb8bf75,0xbcc93f4ebf773ec4,0xbee6bedb3f7abf46,0xbf583f71bea1bf0e,0x3efcbf7d3f393dc9,0xbf6a3e793f1dbf80,0x3f7fbf2cbe2f3f62,
0xbf133f80bf27be48,0x3dfbbf5c3f6fbe95,0xbf803f183e89bf6d,0x3f65bf673e603f22,0xbf09beac3f73bf55,0x3f5fbe16bf313f7f,0x3ecfbf783f4a8000,0x3d973f3ebf7c3ef1,
0x3f62be48bf223f80,0xbf7f3f0e3e95bf6d,0x3f75bf553dc93f35,0xbf463f7bbef1bec4,0x3ef1bf7b3f460000,0xbdc93f55bf753ec4,0xbe95bf0e3f7fbf35,0x3f223e48bf623f6d,
0xbef13f7bbf468000,0x3dc9bf553f75bec4,0x3e953f0ebf7f3f35,0xbf22be483f62bf6d,0x3f62be48bf223f80,0xbf7f3f0e3e95bf6d,0x3f75bf553dc93f35,0xbf463f7bbef1bec4,
0xbf803f2c3dfbbf55,0x3f73bf5c3e2f3f22,0xbf583e163f27bf80,0x3f77bedbbecf3f75,0xbeb83f71bf5f3e48,0x3d97bf4e3f7abef1,0xbf513f78bee6bec4,0x3f1dbf803f313dc9,
0xbcc9bf3e3f7ebf0e,0x3ea13f04bf7c3f46,0x3f09bf7d3f428000,0xbe893f67bf6a3e95,0xbf6f3eac3efcbf7b,0x3f7fbf18be603f62,0xbf13be793f65bf6d,0x3f4abd49bf393f7f,
0x3f7dbf463d493f35,0xbf713f62be79bf0e,0x3f5cbf753edb3ec4,0xbf3e3f7fbf18be48,0x3f4ebdc9bf2c3f80,0xbf673e953f04bf7b,0x3f78bef1beac3f6d,0xbf803f223e16bf55,
0x3e163f22bf803f35,0xbeacbef13f78bf55,0x3f043e95bf673f6d,0xbf2cbdc93f4ebf7b,0xbf183f7fbf3e8000,0x3edbbf753f5cbe48,0xbe793f62bf713ec4,0x3d49bf463f7dbf0e,
0xbf7e3f183e2fbf55,0x3f80bf2cbd973f46,0xbf733edb3eb8bf6d,0x3f7abf04be893f62,0xbf5f3e793f09bf7b,0x3f6abeacbee63f75,0xbf423d493f31bf80,0x3f51be16bf1d3f7f,
0x3dfbbf4e3f7cbf0e,0xbcc93f3ebf7f3f22,0x3ea1bf673f6fbec4,0xbe603f5cbf773ef1,0x3efcbf783f58be48,0xbecf3f71bf653e95,0x3f27bf803f398000,0xbf133f7dbf4a3dc9,
0xbf8000003f80,0xbf8000003f80,0xbf8000003f80,0xbf8000003f80,0xbf8000003f80,0xbf8000003f80,0xbf8000003f80,0xbf8000003f80,
0x3f808000bf808000,0x3f808000bf808000,0x3f808000bf808000,0x3f808000bf808000,0x3f808000bf808000,0x3f808000bf808000,0x3f808000bf808000,0x3f808000bf808000,
0xbf5f3f043f58bf0e,0xbf6a3edb3f65bef1,0xbf423f2c3f39bf35,0xbf513f183f4abf22,0xbf7e3e163f7cbe48,0xbf803d493f7fbdc9,0xbf733eac3f6fbec4,0xbf7a3e793f77be95,
0xbefcbf5c3f093f55,0xbecfbf673ee63f62,0xbf27bf3e3f313f35,0xbf13bf4e3f1d3f46,0xbdfbbf7d3e2f3f7b,0xbcc9bf803d973f7f,0xbea1bf713eb83f6d,0xbe60bf783e893f75,
0x3f183f46bf2cbf35,0x3edb3f62bf04bf55,0x3e793f75beacbf6d,0x3d493f7fbe16bf7b,0x3f7d3dc9bf800000,0x3f713e95bf78be48,0x3f5c3ef1bf67bec4,0x3f3e3f22bf4ebf0e,
0xbf4e3f223f3ebf35,0xbf673ef13f5cbf0e,0xbf783e953f71bec4,0xbf803dc93f7dbe48,0xbe163f7f3d49bf80,0xbeac3f753e79bf7b,0xbf043f623edbbf6d,0xbf2c3f463f18bf55,
0x3f6fbedbbf5f3f0e,0x3f7fbe16bf7a3e95,0x3f13bf5cbee63f6d,0x3f4abf2cbf313f46,0x3cc9bf803dfb3f7b,0x3ea1bf78be2f3f7f,0xbf09bf4e3f273f35,0xbe89bf713ecf3f62,
0x3eb83f67befcbf55,0x3d973f7dbe60bf75,0x3f513f04bf65bec4,0x3f1d3f3ebf39bf22,0x3f80bd49bf7e3e48,0x3f733e79bf7cbdc9,0x3f58bf18bf423f35,0x3f77beacbf6a3ef1,
0xbe953f7b3dc9bf80,0xbf223f553ef1bf6d,0xbf623f0e3f46bf35,0xbf7f3e483f75bec4,0xbf75be483f7f0000,0xbf46bf0e3f623ec4,0xbef1bf553f223f35,0xbdc9bf7b3e953f6d,
0xbf75be483f7f8000,0xbf46bf0e3f623ec4,0xbef1bf553f223f35,0xbdc9bf7b3e953f6d,0x3e95bf7bbdc93f80,0x3f22bf55bef13f6d,0x3f62bf0ebf463f35,0x3f7fbe48bf753ec4,
0x3f583edbbf73be48,0x3efc3f4ebf31bf22,0x3f6abf04bf4a3f35,0x3f7fbd49bf7c3e95,0xbf513f2c3f27bf55,0xbf7e3e793f6fbef1,0x3cc93f7dbe89bf6d,0xbee63f713e60bf7f,
0xbf093f673ea1bf7b,0xbf5f3f183f39bf46,0x3ecf3f5cbf1dbf35,0xbd973f80be2fbf75,0xbf13bf3e3f423f0e,0xbdfbbf783eb83f62,0xbf803e163f77bec4,0xbf65beac3f7a3dc9,
0x3f71bef1bf4e3f35,0x3f783dc9bf803e48,0x3f2c3f22bf5cbec4,0x3e163f75bedbbf55,0xbf67be953f7d0000,0xbf04bf463f3e3f0e,0x3d49bf7f3e793f6d,0x3f18bf62beac3f7b,
0x3eac3f62bf18bf35,0xbe793f7fbd49bf7b,0xbf3e3f463f04bf6d,0xbf7d3e953f67bf0e,0x3edbbf75be163f80,0x3f5cbf22bf2c3f55,0x3f80bdc9bf783ec4,0x3f4e3ef1bf71be48,
0x3f27bf5cbeb83f7b,0x3f7cbeacbf5f3f22,0xbf1dbf2c3f583ec4,0x3cc9bf7d3ea13f62,0xbf653f183f31bf55,0xbf7abd493f7ebe95,0x3e893f67bf13bf35,0xbecf3f783d97bf7f,
0x3f423f04bf6fbe48,0x3e2f3f71befcbf46,0x3f4abf3ebf093f6d,0x3f80be16bf733ef1,0xbee6bf4e3f393f0e,0x3e60bf803dfb3f75,0xbf773edb3f51bf35,0xbf6abe793f7fbdc9,
0x3f0ebf6dbe483f80,0x3f7bbec4bf553f35,0x3f553ec4bf7b0000,0x3e483f6dbf0ebf35,0xbf0e3f6d3e48bf80,0xbf7b3ec43f55bf35,0xbf55bec43f7b0000,0xbe48bf6d3f0e3f35,
0x3f553ec4bf7b8000,0x3e483f6dbf0ebf35,0xbf0e3f6d3e48bf80,0xbf7b3ec43f55bf35,0xbf55bec43f7b8000,0xbe48bf6d3f0e3f35,0x3f0ebf6dbe483f80,0x3f7bbec4bf553f35,
0x3d97bf7d3eb83f55,0x3f51bf3ebefc3f75,0xbf7e3eac3f58bf35,0xbf39bf043f733dc9,0xbee63f783cc9bf7b,0xbf7a3edb3f4abf46,0x3f773d49bf7c3ec4,0x3ecf3f4ebf42bef1,
0x3f7fbe16bf6f3f0e,0x3f133f2cbf5fbe95,0xbdfbbf713f093f35,0x3f31bf5cbea13f7f,0xbf65be793f80be48,0xbe60bf673f1d3f22,0xbe893f80be2fbf6d,0xbf6a3f183f27bf62,
0xbd49bf753f043f35,0x3f4ebf46bedb3f7b,0x3f713dc9bf7d3ec4,0x3e793f62bf2cbf0e,0x3f3e3ef1bf780000,0xbe163f7fbeacbf55,0xbf673f223f18bf6d,0xbf5cbe953f80be48,
0x3f80be95bf5c3f35,0x3f183f22bf67be48,0xbeac3f7fbe16bf6d,0xbf783ef13f3ebf55,0xbf2c3f623e79bf80,0xbf7d3dc93f71bf0e,0xbedbbf463f4e3ec4,0x3f04bf75bd493f7b,
0x3e60bf803ea13f55,0x3f77bf04bf313f62,0xbf6f3f183f1dbf6d,0xbf42bedb3f7cbdc9,0x3f513eacbf7f3e48,0xbdfb3f7dbecfbf46,0x3cc9bf783efc3f35,0x3f65bf2cbf093f75,
0x3f7abd49bf733f0e,0x3e893f5cbf39bef1,0xbeb8bf4e3f4a3ec4,0x3f27bf67be2f3f7f,0xbf133f713d97bf7b,0xbf7e3e163f6abf22,0x3f80be79bf5f3f35,0x3ee63f3ebf58be95,
0xbf463f553e95bf80,0xbf62be483f7fbec4,0x3dc9bf7b3ef13f35,0x3f75bf0ebf223f6d,0x3f223f0ebf750000,0xbef13f7bbdc9bf6d,0xbf7f3e483f62bf35,0xbe95bf553f463ec4,
0xbf22bf0e3f758000,0x3ef1bf7b3dc93f6d,0x3f7fbe48bf623f35,0x3e953f55bf46bec4,0xbf463f553e95bf80,0xbf62be483f7fbec4,0x3dc9bf7b3ef13f35,0x3f75bf0ebf223f6d,
0xbf6a3f2c3efcbf7b,0xbf27bf043f7abdc9,0x3f7cbe16bf653f35,0x3dfb3f67bf31bef1,0x3cc93f71bf1dbf0e,0xbf733f183f13bf75,0x3f09bf783d973f6d,0x3f77bd49bf6f3f22,
0xbecfbf3e3f5f3e48,0x3f42bf5cbe603f7f,0xbe2f3f7dbee6bf35,0xbf7e3edb3f39bf62,0xbf803eac3f4abf55,0xbea1bf4e3f513e95,0x3f583e79bf7f3ec4,0xbe893f80beb8bf46,
0xbf783dc93f67bf35,0x3d49bf753f183f0e,0x3f7dbef1bf2c3f6d,0x3eac3f46bf5cbe48,0xbf04bf223f710000,0x3f3ebf62be163f7b,0x3f4e3e95bf803ec4,0xbedb3f7fbe79bf55,
0x3e79bf7f3edb3f35,0x3f80be95bf4e3f55,0x3e163f62bf3ebec4,0xbf713f223f04bf7b,0x3f5cbf46beac3f80,0x3f2c3ef1bf7d3e48,0xbf183f75bd49bf6d,0xbf67bdc93f78bf0e,
0xbe89bf4e3f583e48,0x3f6fbf2cbee63f7f,0x3d973f67bf39bec4,0xbf7c3f043f1dbf75,0x3dfbbf783f133f0e,0x3f80beacbf423f62,0xbea13f80becfbf35,0xbf7a3e163f5fbf46,
0x3f77bf18bf093f7b,0x3eb83f3ebf65bdc9,0xbf7f3edb3f31bf6d,0xbe2fbf5c3f4a3e95,0x3f7ebe79bf513f55,0xbcc93f71bf27bef1,0xbf733d493f6abf35,0x3e60bf7d3efc3f22,
0x3f6dbf35bec43f80,0x3ec43f35bf6d0000,0xbf6d3f353ec4bf80,0xbec4bf353f6d0000,0x3f6dbf35bec43f80,0x3ec43f35bf6d0000,0xbf6d3f353ec4bf80,0xbec4bf353f6d0000,
0x3ec43f35bf6d8000,0xbf6d3f353ec4bf80,0xbec4bf353f6d8000,0x3f6dbf35bec43f80,0x3ec43f35bf6d8000,0xbf6d3f353ec4bf80,0xbec4bf353f6d8000,0x3f6dbf35bec43f80,
0x3f4a3e79bf7c3f0e,0xbf313f71bd97bf62,0xbf65bd493f6fbf35,0x3f09bf7d3e893f46,0x3efc3f18bf7a3e48,0xbf6a3f3e3ea1bf7f,0xbf27bedb3f80bec4,0x3f51bf5cbdfb3f75,
0xbf1d3f78be2fbf55,0xbf39beac3f7fbef1,0x3ee6bf803eb83f35,0x3f583e16bf773f22,0xbf5f3f4e3e60bf7b,0xbecfbf2c3f73bdc9,0x3f42bf67bcc93f6d,0x3f133f04bf7e3e95,
0xbf043f7fbeacbf35,0xbf3ebe953f7dbf0e,0x3f4ebf62bd493f6d,0x3edb3f22bf783e48,0x3e793f46bf670000,0xbf803ef13f18bf7b,0x3e16bf753f2c3ec4,0x3f71bdc9bf5c3f55,
0xbf5cbdc93f71bf35,0x3f2cbf753e163f55,0x3f183ef1bf803ec4,0xbf673f463e79bf7b,0xbf783f223edbbf80,0xbd49bf623f4e3e48,0x3f7dbe95bf3e3f6d,0xbeac3f7fbf04bf0e,
0xbf31beac3f7ebf0e,0x3f65bf4ebe2f3f75,0x3f7abe79bf423f6d,0xbefc3f80becfbf22,0xbf6f3f3e3e89bf7b,0xbd97bf5c3f583dc9,0x3f13bf7d3ea13f35,0x3f1d3edbbf803ef1,
0x3f39bf713dfb3f55,0x3ee63f18bf7c3e95,0xbe603f78bf27bec4,0xbf5fbd493f6abf46,0xbeb8bf2c3f77be48,0x3f7fbf04bf093f7f,0x3f513e16bf733f35,0xbf4a3f67bcc9bf62,
0xbf7f3f0e3ef1bf80,0x3e95bf7b3f223ec4,0x3f463e48bf753f35,0xbf623f553dc9bf6d,0xbdc9bf553f620000,0x3f75be48bf463f6d,0xbf223f7bbe95bf35,0xbef1bf0e3f7fbec4,
0xbdc9bf553f628000,0x3f75be48bf463f6d,0xbf223f7bbe95bf35,0xbef1bf0e3f7fbec4,0x3f7fbf0ebef13f80,0xbe953f7bbf22bec4,0xbf46be483f75bf35,0x3f62bf55bdc93f6d,
0x3e2fbf713f423e48,0x3f4a3e16bf6f3f46,0x3f393e79bf773f35,0xbf733f3e3e60bf75,0x3f583d49bf653f55,0xbf5f3f5c3cc9bf62,0xbf6a3f4e3dfbbf6d,0x3d97bf673f513dc9,
0x3f7cbeacbf273f7b,0xbf1d3f7dbeb8bf22,0xbf313f78be89bf35,0xbea1bf2c3f7abe95,0xbf093f80bee6bf0e,0xbefcbf043f80bef1,0xbecfbf183f7ebec4,0x3f7fbedbbf133f7f,
0x3f2c3e95bf783f35,0xbf7d3f223eacbf7b,0x3edbbf7f3f183ec4,0x3f043ef1bf803f0e,0x3d49bf623f5c0000,0x3f4e3dc9bf673f55,0xbf713f463e16bf6d,0x3e79bf753f3e3e48,
0xbf3e3f75be79bf35,0xbe16bf463f71be48,0x3f67bdc9bf4e3f6d,0xbf5c3f62bd49bf55,0x3f80bef1bf043f80,0xbf183f7fbedbbf0e,0xbeacbf223f7dbec4,0x3f78be95bf2c3f7b,
0xbf733e793f31bf7b,0x3f58bf673dfb3f46,0x3efcbf803f133ec4,0x3eb83f18bf7f3ef1,0x3f423e16bf6a3f55,0xbf7c3f2c3e89bf75,0xbf4a3f71be60bf35,0x3cc9bf5c3f65bdc9,
0x3ea1bf783f393e48,0x3f093edbbf7e3f22,0x3f5fbd49bf513f6d,0xbf6f3f4e3d97bf62,0xbf273f7dbecfbf0e,0xbe2fbf3e3f77be95,0xbf1dbeac3f7abf35,0x3f80bf04bee63f7f,
0x3f7bbec4bf0e3f80,0xbf553f6dbe48bf35,0x3e48bf6d3f550000,0x3f0e3ec4bf7b3f35,0xbf7b3ec43f0ebf80,0x3f55bf6d3e483f35,0xbe483f6dbf550000,0xbf0ebec43f7bbf35,
0xbe483f6dbf558000,0xbf0ebec43f7bbf35,0x3f7bbec4bf0e3f80,0xbf553f6dbe48bf35,0x3e48bf6d3f558000,0x3f0e3ec4bf7b3f35,0xbf7b3ec43f0ebf80,0x3f55bf6d3e483f35,
0xbf733f4e3cc9bf55,0x3f09bf803f1d3e95,0xbefcbedb3f7cbf35,0x3f6fbe79bf273f7f,0x3f7fbf04becf3f7b,0xbf513f71be89bf22,0x3dfb3f3ebf7a3ec4,0xbf39be163f65bf62,
0xbea1bf183f80bf0e,0x3f58bd49bf4a3f75,0x3f5fbf673e2f3f35,0xbeb83f78bf42bdc9,0xbd973f5cbf6a3e48,0xbf13beac3f77bf46,0xbf7e3f2c3e60bf6d,0x3f31bf7d3ee63ef1,
0x3f67bf623e163f35,0xbf043f7fbf2cbe48,0xbd49bf463f78bec4,0x3f183e95bf713f55,0xbeac3f75bf4e0000,0xbe79bf223f80bf0e,0x3f3e3dc9bf5c3f6d,0xbf7d3ef13edbbf7b,
0x3edb3ef1bf7d3f35,0xbf5c3dc93f3ebf7b,0x3f80bf22be793f6d,0xbf4e3f75beacbf0e,0xbf713e953f18bf80,0x3f78bf46bd493f55,0xbf2c3f7fbf04bec4,0x3e16bf623f67be48,
0xbf7c3f3e3d97bf55,0x3f4abf783ecf3ef1,0xbf31be163f5fbf6d,0x3f73beacbf093f7f,0x3e60bf673f65be48,0x3e893f18bf803f22,0x3f6fbf5c3dfb3f35,0xbf273f80bf13be95,
0xbe2fbf2c3f7fbf0e,0x3f1d3e79bf6a3f62,0x3f39bf7d3efc3ec4,0xbea13f71bf583dc9,0x3f7abedbbee63f7b,0xbf773f4ebcc9bf46,0x3eb83f04bf7e3f35,0xbf42bd493f51bf75,
0xbf623e483f22bf80,0x3f7fbf0ebe953f6d,0xbf753f55bdc9bf35,0x3f46bf7b3ef13ec4,0xbef13f7bbf460000,0x3dc9bf553f75bec4,0x3e953f0ebf7f3f35,0xbf22be483f62bf6d,
0x3ef1bf7b3f468000,0xbdc93f55bf753ec4,0xbe95bf0e3f7fbf35,0x3f223e48bf623f6d,0xbf623e483f22bf80,0x3f7fbf0ebe953f6d,0xbf753f55bdc9bf35,0x3f46bf7b3ef13ec4,
0x3f393d49bf4a3f7b,0xbf653e793f13bf7f,0x3e603f18bf7f3f35,0xbefcbeac3f6fbf62,0x3f6abf673e893f0e,0xbf423f7dbf09be95,0x3f7cbf04bea13f6d,0xbf7e3f3e3cc9bf46,
0xbf313f80bf1dbe48,0x3ee6bf783f51bdc9,0xbf7a3f4ebd97bf35,0x3f5fbf713eb83ef1,0x3ecf3edbbf773f55,0xbf27be163f58bf75,0xbe2f3f5cbf733ec4,0xbdfbbf2c3f80bf22,
0xbe16bf223f80bf35,0x3eac3ef1bf783f55,0xbf04be953f67bf6d,0x3f2c3dc9bf4e3f7b,0x3f18bf7f3f3e0000,0xbedb3f75bf5c3e48,0x3e79bf623f71bec4,0xbd493f46bf7d3f0e,
0x3f7dbf463d493f35,0xbf713f62be79bf0e,0x3f5cbf753edb3ec4,0xbf3e3f7fbf18be48,0x3f4ebdc9bf2c3f80,0xbf673e953f04bf7b,0x3f78bef1beac3f6d,0xbf803f223e16bf55,
0xbf4a3f7dbf13be48,0x3f39bf803f273dc9,0xbf653f71becfbec4,0x3f58bf783efc3e95,0xbf773f5cbe60bf0e,0x3f6fbf673ea13ef1,0xbf7f3f3ebcc9bf35,0x3f7cbf4e3dfb3f22,
0xbf1dbe163f51bf7b,0x3f313d49bf423f7f,0xbee6beac3f6abf6d,0x3f093e79bf5f3f75,0xbe89bf043f7abf55,0x3eb83edbbf733f62,0xbd97bf2c3f80bf35,0x3e2f3f18bf7e3f46,
0xbf3500003f353f80,0x3f350000bf35bf80,0xbf3500003f353f80,0x3f350000bf35bf80,0xbf3500003f353f80,0x3f350000bf35bf80,0xbf3500003f353f80,0x3f350000bf35bf80,
0xbf35bf80bf358000,0x3f353f803f358000,0xbf35bf80bf358000,0x3f353f803f358000,0xbf35bf80bf358000,0x3f353f803f358000,0xbf35bf80bf358000,0x3f353f803f358000,
0x3f77bf783f7abf7b,0x3f6fbf713f73bf75,0x3f7fbf803f80bf80,0x3f7cbf7d3f7ebf7f,0x3f4abf4e3f51bf55,0x3f39bf3e3f42bf46,0x3f65bf673f6abf6d,0x3f58bf5c3f5fbf62,
0xbe893e79be603e48,0xbeb83eacbea13e95,0xbd973d49bcc98000,0xbe2f3e16bdfb3dc9,0xbf1d3f18bf133f0e,0xbf313f2cbf273f22,0xbee63edbbecf3ec4,0xbf093f04befc3ef1,
0xbf183f22bf2c3f35,0xbedb3ef1bf043f0e,0xbe793e95beac3ec4,0xbd493dc9be163e48,0xbf7d3f7fbf803f80,0xbf713f75bf783f7b,0xbf5c3f62bf673f6d,0xbf3e3f46bf4e3f55,
0x3f4ebf463f3ebf35,0x3f67bf623f5cbf55,0x3f78bf753f71bf6d,0x3f80bf7f3f7dbf7b,0x3e16bdc93d498000,0x3eacbe953e79be48,0x3f04bef13edbbec4,0x3f2cbf223f18bf0e,
0xbecf3eacbe893e48,0xbf273f18bf093ef1,0x3e2fbe793ea1bec4,0xbdfb3d493cc9bdc9,0x3f31bf3e3f4abf55,0x3ee6bf043f13bf22,0x3f7abf7d3f7fbf80,0x3f5fbf673f6fbf75,
0xbf6a3f71bf773f7b,0xbf423f4ebf583f62,0xbf7c3f78bf733f6d,0xbf7e3f80bf803f7f,0xbf393f2cbf1d3f0e,0xbf653f5cbf513f46,0xbe603e16bd978000,0xbefc3edbbeb83e95,
0xbf753f7bbf7f3f80,0xbf463f55bf623f6d,0xbef13f0ebf223f35,0xbdc93e48be953ec4,0x3e95be483dc90000,0x3f22bf0e3ef1bec4,0x3f62bf553f46bf35,0x3f7fbf7b3f75bf6d,
0x3e95be483dc98000,0x3f22bf0e3ef1bec4,0x3f62bf553f46bf35,0x3f7fbf7b3f75bf6d,0x3f75bf7b3f7fbf80,0x3f46bf553f62bf6d,0x3ef1bf0e3f22bf35,0x3dc9be483e95bec4,
0x3e60beac3ee6bf0e,0xbe893e16bcc9bdc9,0x3f6fbf783f7ebf80,0x3f27bf3e3f51bf62,0xbf7c3f80bf7f3f7b,0xbf4a3f5cbf6a3f75,0xbf313f18befc3ec4,0xbf733f67bf583f46,
0xbf7a3f71bf653f55,0xbf773f7dbf803f7f,0xbeb83e79bdfb8000,0xbf423f2cbf133ef1,0x3e2fbd49bd973e48,0x3f1dbf043ecfbe95,0xbf393f4ebf5f3f6d,0xbea13edbbf093f22,
0x3f71bf623f4ebf35,0x3f78bf7f3f80bf7b,0x3f2cbf463f5cbf6d,0x3e16be953edbbf0e,0xbf673f75bf7d3f80,0xbf043f22bf3e3f55,0x3d493dc9be793ec4,0x3f18bef13eacbe48,
0x3eacbef13f18bf35,0xbe793dc93d49be48,0xbf3e3f22bf043ec4,0xbf7d3f75bf673f55,0x3edbbe953e168000,0x3f5cbf463f2cbf0e,0x3f80bf7f3f78bf6d,0x3f4ebf623f71bf7b,
0xbd973e79becf3f0e,0x3f13bedb3e89bdc9,0xbf7e3f80bf7a3f6d,0xbf313f4ebf653f75,0xbea13e163cc9be48,0xbf583f3ebf1d3ef1,0x3f5fbf713f7cbf80,0x3eb8bf043f27bf46,
0x3f7fbf783f6abf55,0x3f51bf673f77bf7f,0x3dfb3d49be603ec4,0x3f39bf183ee6be95,0xbf733f7dbf803f7b,0xbf093f2cbf4a3f62,0xbefc3eacbe2f8000,0xbf6f3f5cbf423f22,
0xbf553f6dbf7b3f80,0xbe483ec4bf0e3f35,0x3f0ebec43e480000,0x3f7bbf6d3f55bf35,0x3f55bf6d3f7bbf80,0x3e48bec43f0ebf35,0xbf0e3ec4be480000,0xbf7b3f6dbf553f35,
0x3f0ebec43e488000,0x3f7bbf6d3f55bf35,0x3f55bf6d3f7bbf80,0x3e48bec43f0ebf35,0xbf0e3ec4be488000,0xbf7b3f6dbf553f35,0xbf553f6dbf7b3f80,0xbe483ec4bf0e3f35,
0xbf423f18becf3e48,0xbf7c3f80bf773f62,0x3f4abf673f7abf80,0x3cc9be793ee6bf22,0x3f73bf5c3f39bf0e,0x3f58bf713f7ebf7f,0xbefc3f2cbf513f6d,0x3eb8be16bd973e95,
0xbf273f4ebf6a3f7b,0x3e2f3d49be893ef1,0xbf1d3edbbe608000,0xbf803f78bf653f46,0x3ea1bf043f31bf55,0xbf093eacbdfbbdc9,0x3f5fbf3e3f13bec4,0x3f6fbf7d3f7fbf75,
0x3d49be953f04bf35,0xbf4e3f22bedb3e48,0xbf713f7fbf7d3f6d,0xbe793ef1bf2c3f55,0xbf3e3f62bf783f80,0x3e163dc9beac3f0e,0x3f67bf463f18bec4,0x3f5cbf753f80bf7b,
0xbf803f75bf5c3f35,0xbf183f46bf673f7b,0x3eacbdc9be163ec4,0x3f78bf623f3ebf0e,0x3f2cbef13e798000,0x3f7dbf7f3f71bf55,0x3edbbf223f4ebf6d,0xbf043e95bd49be48,
0x3f09bf3e3f65bf7b,0xbefc3e793cc9be95,0x3ecfbe16bdfb3ec4,0x3f7fbf713f51bf22,0xbf7c3f67bf423f0e,0xbf1d3f4ebf6f3f7f,0x3f31bf5c3f77bf80,0xbea13d493e60bef1,
0xbf583f2cbee63e48,0xbf5f3f78bf803f75,0x3f6abf7d3f7ebf6d,0x3d97beac3f13bf46,0xbe2f3edbbf273f55,0x3f4abf183eb8bdc9,0xbf393f04be898000,0xbf733f80bf7a3f62,
0xbf223f55bf753f80,0x3ef1be48bdc93ec4,0x3f7fbf7b3f62bf35,0x3e95bf0e3f46bf6d,0xbf463f0ebe950000,0xbf623f7bbf7f3f6d,0x3dc93e48bef13f35,0x3f75bf553f22bec4,
0x3f46bf0e3e958000,0x3f62bf7b3f7fbf6d,0xbdc9be483ef1bf35,0xbf753f55bf223ec4,0xbf223f55bf753f80,0x3ef1be48bdc93ec4,0x3f7fbf7b3f62bf35,0x3e95bf0e3f46bf6d,
0xbf6f3f80bf773f55,0x3d973e79bf093f46,0x3f13bf4e3f73bf80,0xbf1d3eacbcc9be95,0xbf313edbbdfbbe48,0xbf653f7dbf7c3f62,0x3f7abf5c3f27bec4,0x3efcbf3e3f6abf7f,
0x3eb8bd49be893f0e,0x3f7fbf783f58bf22,0xbf513f18bea18000,0xbf4a3f71bf803f75,0xbf393f67bf7e3f7b,0x3ee6be16be2f3ef1,0x3e60bf043f42bf6d,0xbf5f3f2cbecf3dc9,
0xbf783f7fbf673f35,0x3d493e95bf183f55,0x3f7dbf623f2cbec4,0x3eacbf223f5cbf7b,0xbf043f46bf713f80,0x3f3ebef13e163e48,0x3f4ebf753f80bf6d,0xbedb3dc93e79bf0e,
0x3e793dc9bedb3f35,0x3f80bf753f4ebf0e,0x3e16bef13f3ebf6d,0xbf713f46bf043e48,0x3f5cbf223eac8000,0x3f2cbf623f7dbf7b,0xbf183e953d49bec4,0xbf673f7fbf783f55,
0xbf5f3f7dbf7a3f55,0x3ecfbd49bea13f22,0x3f42bf713f80bf6d,0xbf133e793dfbbef1,0xbf1d3f5cbf7c3f7b,0x3f39bedb3d973e95,0x3ee6bf3e3f6fbf80,0xbf583f18be89bdc9,
0x3efcbe16be603f0e,0x3f6abf803f73bf46,0xbf273eac3cc9bec4,0xbf513f78bf7e3f62,0x3f4abf043e2f3e48,0x3f31bf673f7fbf75,0xbf653f2cbeb88000,0xbf093f4ebf773f7f,
0xbec43f35bf6d3f80,0x3f6dbf353ec40000,0x3ec4bf353f6dbf80,0xbf6d3f35bec40000,0xbec43f35bf6d3f80,0x3f6dbf353ec40000,0x3ec4bf353f6dbf80,0xbf6d3f35bec40000,
0x3f6dbf353ec48000,0x3ec4bf353f6dbf80,0xbf6d3f35bec48000,0xbec43f35bf6d3f80,0x3f6dbf353ec48000,0x3ec4bf353f6dbf80,0xbf6d3f35bec48000,0xbec43f35bf6d3f80,
0xbdfb3f04bf513f7b,0x3f80bf673f27be95,0x3ea1bf2c3f6abf80,0xbf7a3f4ebefc3dc9,0x3e893e16bf093f55,0x3f6fbf803f65bf22,0xbd97beac3f31bf6d,0xbf7c3f78bf4a3ef1,
0x3f7ebf5c3f13be48,0x3cc9bedb3f42bf75,0xbf733f3ebecf8000,0xbe603f18bf5f3f7f,0x3f77bf7d3f58bf0e,0xbeb8bd493ee6bf46,0xbf7f3f71bf393ec4,0x3e2f3e79bf1d3f62,
0x3f04bdc9beac3f35,0x3f3ebf753f7dbf55,0xbf4e3ef1bd49bec4,0xbedb3f46bf783f7b,0xbe793f22bf673f80,0x3f80bf623f18be48,0xbe16be953f2cbf6d,0xbf713f7fbf5c3f0e,
0x3f5cbf7f3f71bf35,0xbf2c3e953e16bf0e,0xbf183f62bf803f6d,0x3f67bf223e793e48,0x3f78bf463edb8000,0x3d49bef13f4ebf7b,0xbf7d3f75bf3e3ec4,0x3eac3dc9bf043f55,
0x3f80bf673f1dbe48,0xbea1be163f13bf62,0xbf583f04bd97bec4,0xbe893f2cbf6f3f7f,0x3ecf3d49befc3f55,0x3f42bf783f7abf46,0x3e2fbf183f65bf80,0xbf7e3f71bf313e95,
0xbcc9bedb3f4abf7b,0xbf733f7dbf513ef1,0xbf093f5cbf7f3f6d,0x3f77bf3e3eb83dc9,0x3f6abf803f5fbf0e,0xbf273e793e60bf22,0xbf7c3f4ebee68000,0x3dfb3eacbf393f75,
0xbdc93f0ebf623f80,0x3f75bf7b3f46bec4,0xbf223e483e95bf35,0xbef13f55bf7f3f6d,0x3f7fbf553ef10000,0xbe95be483f22bf6d,0xbf463f7bbf753f35,0x3f62bf0e3dc93ec4,
0x3f7fbf553ef18000,0xbe95be483f22bf6d,0xbf463f7bbf753f35,0x3f62bf0e3dc93ec4,0x3dc9bf0e3f62bf80,0xbf753f7bbf463ec4,0x3f22be48be953f35,0x3ef1bf553f7fbf6d,
0x3f51bedbbd973f0e,0x3dfbbf183f6abf7f,0x3cc9bf043f5fbf80,0xbf653f80bf583ef1,0x3e60bf2c3f73bf7b,0xbf773f78bf393e95,0xbf6f3f7dbf4a3ec4,0x3f42beacbe2f3f22,
0x3f13bf673f7fbf55,0xbf7e3f4ebecfbdc9,0xbf803f5cbefc8000,0x3ee63d49bf093f62,0xbf7a3f3ebea1be48,0x3e893e79bf313f75,0x3eb83e16bf1d3f6d,0x3f27bf713f7cbf46,
0x3f2cbf753f78bf35,0xbf7d3f46beacbe48,0x3edb3dc9bf183f6d,0x3f04bf623f80bf55,0x3d493ef1bf5c3f80,0x3f4ebf7f3f67bf0e,0xbf713f22be16bec4,0x3e793e95bf3e3f7b,
0xbf3e3e953e79bf35,0xbe163f22bf713f7b,0x3f67bf7f3f4ebec4,0xbf5c3ef13d49bf0e,0x3f80bf623f048000,0xbf183dc93edbbf55,0xbeac3f46bf7d3f6d,0x3f78bf753f2cbe48,
0xbf653f043cc9bf0e,0x3e603eacbf4a3f7f,0xbe893f3ebf7c3f6d,0x3f6abf7d3f42be95,0x3f7fbf4e3eb83e48,0xbf133d493efcbf62,0xbdfbbedb3f58bf80,0xbf313f78bf733f22,
0xbee63f5cbf803f55,0x3f7abf713f1dbdc9,0x3f77bf2c3e2f3ec4,0xbecfbe163f27bf75,0x3d97bf183f6fbf7b,0xbf513f80bf5f3ef1,0xbf7e3f67bf098000,0x3f39be79bea13f46,
0x3e483ec4bf553f80,0x3f0ebf6d3f7bbf35,0xbf7b3f6dbf0e0000,0x3f55bec4be483f35,0xbe48bec43f55bf80,0xbf0e3f6dbf7b3f35,0x3f7bbf6d3f0e0000,0xbf553ec43e48bf35,
0x3f7bbf6d3f0e8000,0xbf553ec43e48bf35,0x3e483ec4bf553f80,0x3f0ebf6d3f7bbf35,0xbf7b3f6dbf0e8000,0x3f55bec4be483f35,0xbe48bec43f55bf80,0xbf0e3f6dbf7b3f35,
0x3f65bf7d3f39be48,0xbf7a3f2cbdfbbef1,0xbe89beac3f51bf80,0xbecf3f5cbf7f3f46,0xbf273f78bf6f3f0e,0x3f7cbf673efc3dc9,0x3f1dbd49bf093f6d,0x3cc9bf183f73bf75,
0xbee6be163f31bf7b,0xbe603f3ebf7e3f62,0xbf773f71bf138000,0x3f6abf04bd973f22,0x3f42be79beb83f55,0xbe2fbedb3f5fbf7f,0x3f4abf803f58bec4,0xbf803f4ebea1be95,
0xbf673ef13e16bf35,0x3f043dc9bf2c3f7b,0x3d49bf223f78bf6d,0xbf183f75bf713f0e,0x3eac3e95bf4e3f80,0x3e79bf463f80bf55,0xbf3e3f7fbf5c3ec4,0x3f7dbf623edb3e48,
0xbedb3f62bf7d3f35,0x3f5cbf7f3f3ebe48,0xbf803f46be79bec4,0x3f4ebe95beac3f55,0x3f71bf753f188000,0xbf783f22bd49bf0e,0x3f2cbdc9bf043f6d,0xbe16bef13f67bf7b,
0x3f133d49bf273f7b,0xbdfbbf043f6fbf75,0x3f80bf4e3e893ec4,0xbf653edb3e60bf46,0x3f09bf713f73bf0e,0xbf5f3f7dbf313dc9,0xbecfbe793f4abf80,0xbd973f2cbf7c3f62,
0x3f51bf803f42be48,0xbf7e3f5cbeb8be95,0xbcc9bf183f77bf6d,0xbee63f67bf7a3f22,0xbf583eac3ea1bf55,0x3efc3e16bf393f7f,0xbf6a3f78bf1d8000,0x3f7fbf3e3e2f3ef1,
0x3ef13e48bf463f80,0xbdc9bf0e3f75bf6d,0xbe953f55bf7f3f35,0x3f22bf7b3f62bec4,0xbf623f7bbf220000,0x3f7fbf553e953ec4,0xbf753f0e3dc9bf35,0x3f46be48bef13f6d,
0x3f62bf7b3f228000,0xbf7f3f55be95bec4,0x3f75bf0ebdc93f35,0xbf463e483ef1bf6d,0x3ef13e48bf463f80,0xbdc9bf0e3f75bf6d,0xbe953f55bf7f3f35,0x3f22bf7b3f62bec4,
0x3cc9bf2c3f7ebf55,0xbea13f5cbf7c3f22,0xbf09be163f42bf80,0x3e893edbbf6a3f75,0x3f6fbf713efc3e48,0xbf7f3f4ebe60bef1,0x3f13bf783f65bec4,0xbf4a3f80bf393dc9,
0xbf803f3ebdfbbf0e,0x3f73bf04be2f3f46,0xbf583f7dbf278000,0x3f77bf673ecf3e95,0xbeb8beac3f5fbf7b,0x3d973f18bf7a3f62,0xbf513e793ee6bf6d,0x3f1d3d49bf313f7f,
0xbe163f46bf803f35,0x3eacbf623f78bf0e,0xbf043f75bf673ec4,0x3f2cbf7f3f4ebe48,0x3f183dc9bf3e3f80,0xbedbbe953f5cbf7b,0x3e793ef1bf713f6d,0xbd49bf223f7dbf55,
0x3f7dbf22bd493f35,0xbf713ef13e79bf55,0x3f5cbe95bedb3f6d,0xbf3e3dc93f18bf7b,0x3f4ebf7f3f2c8000,0xbf673f75bf04be48,0x3f78bf623eac3ec4,0xbf803f46be16bf0e,
0xbdfbbf183f7cbf55,0x3cc93f2cbf7f3f46,0xbea1bedb3f6fbf6d,0x3e603f04bf773f62,0xbefcbe793f58bf7b,0x3ecf3eacbf653f75,0xbf27bd493f39bf80,0x3f133e16bf4a3f7f,
0xbf7e3f4ebe2fbf0e,0x3f80bf3e3d973f22,0xbf733f67beb8bec4,0x3f7abf5c3e893ef1,0xbf5f3f78bf09be48,0x3f6abf713ee63e95,0xbf423f80bf318000,0x3f51bf7d3f1d3dc9,
0xbf3500003f353f80,0x3f350000bf35bf80,0xbf3500003f353f80,0x3f350000bf35bf80,0xbf3500003f353f80,0x3f350000bf35bf80,0xbf3500003f353f80,0x3f350000bf35bf80,
0xbf35bf80bf358000,0x3f353f803f358000,0xbf35bf80bf358000,0x3f353f803f358000,0xbf35bf80bf358000,0x3f353f803f358000,0xbf35bf80bf358000,0x3f353f803f358000,
0x3efcbf043f09bf0e,0x3ecfbedb3ee6bef1,0x3f27bf2c3f31bf35,0x3f13bf183f1dbf22,0x3dfbbe163e2fbe48,0x3cc9bd493d97bdc9,0x3ea1beac3eb8bec4,0x3e60be793e89be95,
0xbf5f3f5cbf583f55,0xbf6a3f67bf653f62,0xbf423f3ebf393f35,0xbf513f4ebf4a3f46,0xbf7e3f7dbf7c3f7b,0xbf803f80bf7f3f7f,0xbf733f71bf6f3f6d,0xbf7a3f78bf773f75,
0x3f4ebf463f3ebf35,0x3f67bf623f5cbf55,0x3f78bf753f71bf6d,0x3f80bf7f3f7dbf7b,0x3e16bdc93d490000,0x3eacbe953e79be48,0x3f04bef13edbbec4,0x3f2cbf223f18bf0e,
0x3f18bf223f2cbf35,0x3edbbef13f04bf0e,0x3e79be953eacbec4,0x3d49bdc93e16be48,0x3f7dbf7f3f80bf80,0x3f71bf753f78bf7b,0x3f5cbf623f67bf6d,0x3f3ebf463f4ebf55,
0xbeb83edbbefc3f0e,0xbd973e16be603e95,0xbf513f5cbf653f6d,0xbf1d3f2cbf393f46,0xbf803f80bf7e3f7b,0xbf733f78bf7c3f7f,0xbf583f4ebf423f35,0xbf773f71bf6a3f62,
0x3f6fbf673f5fbf55,0x3f7fbf7d3f7abf75,0x3f13bf043ee6bec4,0x3f4abf3e3f31bf22,0x3cc93d49bdfb3e48,0x3ea1be793e2fbdc9,0xbf093f18bf273f35,0xbe893eacbecf3ef1,
0x3f75bf7b3f7fbf80,0x3f46bf553f62bf6d,0x3ef1bf0e3f22bf35,0x3dc9be483e95bec4,0xbe953e48bdc90000,0xbf223f0ebef13ec4,0xbf623f55bf463f35,0xbf7f3f7bbf753f6d,
0xbe953e48bdc98000,0xbf223f0ebef13ec4,0xbf623f55bf463f35,0xbf7f3f7bbf753f6d,0xbf753f7bbf7f3f80,0xbf463f55bf623f6d,0xbef13f0ebf223f35,0xbdc93e48be953ec4,
0x3f09bedb3ea1be48,0x3f5fbf4e3f39bf22,0xbecf3f04bf1d3f35,0x3d973d49be2f3e95,0x3f13bf2c3f42bf55,0x3dfbbe793eb8bef1,0x3f80bf7d3f77bf6d,0x3f65bf713f7abf7f,
0x3f58bf673f73bf7b,0x3efcbf183f31bf46,0x3f6abf5c3f4abf35,0x3f7fbf803f7cbf75,0xbf513f3ebf273f0e,0xbf7e3f78bf6f3f62,0x3cc9be163e89bec4,0xbee63eacbe603dc9,
0xbeac3ef1bf183f35,0x3e79bdc9bd493e48,0x3f3ebf223f04bec4,0x3f7dbf753f67bf55,0xbedb3e95be160000,0xbf5c3f46bf2c3f0e,0xbf803f7fbf783f6d,0xbf4e3f62bf713f7b,
0x3f71bf623f4ebf35,0x3f78bf7f3f80bf7b,0x3f2cbf463f5cbf6d,0x3e16be953edbbf0e,0xbf673f75bf7d3f80,0xbf043f22bf3e3f55,0x3d493dc9be793ec4,0x3f18bef13eacbe48,
0xbf423f5cbf6f3f7b,0xbe2f3eacbefc3f22,0xbf4a3f2cbf093ec4,0xbf803f7dbf733f62,0x3ee6bf183f39bf55,0xbe603d493dfbbe95,0x3f77bf673f51bf35,0x3f6abf783f7fbf7f,
0x3f27bf043eb8be48,0x3f7cbf713f5fbf46,0xbf1d3f3ebf583f6d,0x3cc93e16bea13ef1,0xbf653f4ebf313f0e,0xbf7a3f80bf7e3f75,0x3e89bedb3f13bf35,0xbecf3e79bd97bdc9,
0xbf553f6dbf7b3f80,0xbe483ec4bf0e3f35,0x3f0ebec43e480000,0x3f7bbf6d3f55bf35,0x3f55bf6d3f7bbf80,0x3e48bec43f0ebf35,0xbf0e3ec4be480000,0xbf7b3f6dbf553f35,
0x3f0ebec43e488000,0x3f7bbf6d3f55bf35,0x3f55bf6d3f7bbf80,0x3e48bec43f0ebf35,0xbf0e3ec4be488000,0xbf7b3f6dbf553f35,0xbf553f6dbf7b3f80,0xbe483ec4bf0e3f35,
0xbf7f3f7dbf6f3f55,0xbf133f3ebf5f3f75,0x3dfbbeac3f09bf35,0xbf313f04bea13dc9,0x3f65bf783f80bf7b,0x3e60bedb3f1dbf46,0x3e89bd49be2f3ec4,0x3f6abf4e3f27bef1,
0x3d973e16beb83f0e,0x3f51bf2c3efcbe95,0xbf7e3f71bf583f35,0xbf393f5cbf733f7f,0xbee63e79bcc9be48,0xbf7a3f67bf4a3f22,0x3f77bf803f7cbf6d,0x3ecfbf183f42bf62,
0xbf803f75bf5c3f35,0xbf183f46bf673f7b,0x3eacbdc9be163ec4,0x3f78bf623f3ebf0e,0x3f2cbef13e790000,0x3f7dbf7f3f71bf55,0x3edbbf223f4ebf6d,0xbf043e95bd49be48,
0xbd493e95bf043f35,0x3f4ebf223edbbe48,0x3f71bf7f3f7dbf6d,0x3e79bef13f2cbf55,0x3f3ebf623f78bf80,0xbe16bdc93eacbf0e,0xbf673f46bf183ec4,0xbf5c3f75bf803f7b,
0xbf7a3f80bf733f55,0xbe893f04bf393f62,0x3eb8bf183f4abf6d,0xbf273edbbe2fbdc9,0x3f13beac3d973e48,0x3f7ebf7d3f6abf46,0xbf803f78bf5f3f35,0xbee63f2cbf583f75,
0x3e603d49bea13f0e,0x3f77bf5c3f31bef1,0xbf6f3f4ebf1d3ec4,0xbf423f67bf7c3f7f,0x3f51bf713f7fbf7b,0xbdfbbe163ecfbf22,0x3cc93e79befc3f35,0x3f65bf3e3f09be95,
0x3f22bf553f75bf80,0xbef13e483dc9bec4,0xbf7f3f7bbf623f35,0xbe953f0ebf463f6d,0x3f46bf0e3e950000,0x3f62bf7b3f7fbf6d,0xbdc9be483ef1bf35,0xbf753f55bf223ec4,
0xbf463f0ebe958000,0xbf623f7bbf7f3f6d,0x3dc93e48bef13f35,0x3f75bf553f22bec4,0x3f22bf553f75bf80,0xbef13e483dc9bec4,0xbf7f3f7bbf623f35,0xbe953f0ebf463f6d,
0x3ecfbf2c3f5fbf7b,0xbf423f04be60bdc9,0x3e2f3e16bee63f35,0x3f7ebf673f39bef1,0x3f80bf713f4abf0e,0x3ea1bf183f51bf75,0xbf583f78bf7f3f6d,0x3e893d49beb83f22,
0xbf6a3f3ebefc3e48,0xbf273f5cbf7a3f7f,0x3f7cbf7d3f65bf35,0x3dfbbedb3f31bf62,0x3cc9beac3f1dbf55,0xbf733f4ebf133e95,0x3f09be79bd973ec4,0x3f77bf803f6fbf46,
0xbe79bdc93edbbf35,0xbf803f75bf4e3f0e,0xbe163ef1bf3e3f6d,0x3f71bf463f04be48,0xbf5c3f22beac0000,0xbf2c3f62bf7d3f7b,0x3f18be95bd493ec4,0x3f67bf7f3f78bf55,
0xbf783f7fbf673f35,0x3d493e95bf183f55,0x3f7dbf623f2cbec4,0x3eacbf223f5cbf7b,0xbf043f46bf713f80,0x3f3ebef13e163e48,0x3f4ebf753f80bf6d,0xbedb3dc93e79bf0e,
0xbf773f4ebf093e48,0xbeb83f2cbf653f7f,0x3f7fbf673f31bec4,0x3e2fbf043f4abf75,0xbf7e3f78bf513f0e,0x3cc93eacbf273f62,0x3f73bf803f6abf35,0xbe60be163efcbf46,
0xbe893f18bf583f7b,0x3f6fbf3e3ee6bdc9,0x3d97bedb3f39bf6d,0xbf7c3f5cbf1d3e95,0x3dfb3e79bf133f55,0x3f80bf713f42bef1,0xbea1bd493ecfbf35,0xbf7a3f7dbf5f3f22,
0xbec43f35bf6d3f80,0x3f6dbf353ec40000,0x3ec4bf353f6dbf80,0xbf6d3f35bec40000,0xbec43f35bf6d3f80,0x3f6dbf353ec40000,0x3ec4bf353f6dbf80,0xbf6d3f35bec40000,
0x3f6dbf353ec48000,0x3ec4bf353f6dbf80,0xbf6d3f35bec48000,0xbec43f35bf6d3f80,0x3f6dbf353ec48000,0x3ec4bf353f6dbf80,0xbf6d3f35bec48000,0xbec43f35bf6d3f80,
0x3f1dbe79be2f3f0e,0x3f39bf713f7fbf62,0xbee63d493eb8bf35,0xbf583f7dbf773f46,0x3f5fbf183e603e48,0x3ecfbf3e3f73bf7f,0xbf423edbbcc9bec4,0xbf133f5cbf7e3f75,
0x3f4abf783f7cbf55,0xbf313eac3d97bef1,0xbf653f80bf6f3f35,0x3f09be16be893f22,0x3efcbf4e3f7abf7b,0xbf6a3f2cbea1bdc9,0xbf273f67bf803f6d,0x3f51bf043dfb3e95,
0x3f5cbf7f3f71bf35,0xbf2c3e953e16bf0e,0xbf183f62bf803f6d,0x3f67bf223e793e48,0x3f78bf463edb0000,0x3d49bef13f4ebf7b,0xbf7d3f75bf3e3ec4,0x3eac3dc9bf043f55,
0xbf043dc93eacbf35,0xbf3e3f75bf7d3f55,0x3f4ebef13d493ec4,0x3edbbf463f78bf7b,0x3e79bf223f67bf80,0xbf803f62bf183e48,0x3e163e95bf2c3f6d,0x3f71bf7f3f5cbf0e,
0xbf393eac3dfbbf0e,0xbee63f4ebf7c3f75,0x3e603e79bf273f6d,0x3f5fbf803f6abf22,0x3eb8bf3e3f77bf7b,0xbf7f3f5cbf093dc9,0xbf513f7dbf733f35,0x3f4abedbbcc93ef1,
0xbf313f71bf7e3f55,0x3f65bf183e2f3e95,0x3f7abf783f42bec4,0xbefc3d493ecfbf46,0xbf6f3f2cbe89be48,0xbd973f04bf583f7f,0x3f13be16bea13f35,0x3f1dbf673f80bf62,
0x3dc9bf0e3f62bf80,0xbf753f7bbf463ec4,0x3f22be48be953f35,0x3ef1bf553f7fbf6d,0xbf7f3f55bef10000,0x3e953e48bf223f6d,0x3f46bf7b3f75bf35,0xbf623f0ebdc9bec4,
0xbf7f3f55bef18000,0x3e953e48bf223f6d,0x3f46bf7b3f75bf35,0xbf623f0ebdc9bec4,0xbdc93f0ebf623f80,0x3f75bf7b3f46bec4,0xbf223e483e95bf35,0xbef13f55bf7f3f6d,
0xbf7c3f71bf273e48,0x3f1dbe16beb83f46,0x3f31be79be893f35,0x3ea1bf3e3f7abf75,0x3f09bd49bee63f55,0x3efcbf5c3f80bf62,0x3ecfbf4e3f7ebf6d,0xbf7f3f67bf133dc9,
0x3e2f3eacbf423f7b,0x3f4abf7d3f6fbf22,0x3f39bf783f77bf35,0xbf733f2cbe60be95,0x3f58bf803f65bf0e,0xbf5f3f04bcc9bef1,0xbf6a3f18bdfbbec4,0x3d973edbbf513f7f,
0x3f3ebe95be793f35,0x3e16bf223f71bf7b,0xbf673f7fbf4e3ec4,0x3f5cbef1bd493f0e,0xbf803f62bf040000,0x3f18bdc9bedb3f55,0x3eacbf463f7dbf6d,0xbf783f75bf2c3e48,
0x3f2cbf753f78bf35,0xbf7d3f46beacbe48,0x3edb3dc9bf183f6d,0x3f04bf623f80bf55,0x3d493ef1bf5c3f80,0x3f4ebf7f3f67bf0e,0xbf713f22be16bec4,0x3e793e95bf3e3f7b,
0xbea1be793f39bf7b,0xbf093f67bf7e3f46,0xbf5f3f80bf513ec4,0x3f6fbf183d973ef1,0x3f27be16becf3f55,0x3e2fbf2c3f77bf75,0x3f1dbf713f7abf35,0xbf803f5cbee6bdc9,
0xbf733f78bf313e48,0x3f58bedbbdfb3f22,0x3efc3d49bf133f6d,0x3eb8bf4e3f7fbf62,0x3f42bf7d3f6abf0e,0xbf7c3f3ebe89be95,0xbf4a3eac3e60bf35,0x3cc93f04bf653f7f,
0x3e483ec4bf553f80,0x3f0ebf6d3f7bbf35,0xbf7b3f6dbf0e0000,0x3f55bec4be483f35,0xbe48bec43f55bf80,0xbf0e3f6dbf7b3f35,0x3f7bbf6d3f0e0000,0xbf553ec43e48bf35,
0x3f7bbf6d3f0e8000,0xbf553ec43e48bf35,0x3e483ec4bf553f80,0x3f0ebf6d3f7bbf35,0xbf7b3f6dbf0e8000,0x3f55bec4be483f35,0xbe48bec43f55bf80,0xbf0e3f6dbf7b3f35,
0x3ea1bf4e3f80bf55,0xbf583f80bf4a3e95,0xbf5f3edb3e2fbf35,0x3eb83e79bf423f7f,0x3d973f04bf6a3f7b,0x3f13bf713f77bf22,0x3f7ebf3e3e603ec4,0xbf313e163ee6bf62,
0xbf733f18bcc9bf0e,0x3f093d49bf1d3f75,0xbefc3f67bf7c3f35,0x3f6fbf783f27bdc9,0x3f7fbf5c3ecf3e48,0xbf513eac3e89bf46,0x3dfbbf2c3f7abf6d,0xbf393f7dbf653ef1,
0xbedb3f62bf7d3f35,0x3f5cbf7f3f3ebe48,0xbf803f46be79bec4,0x3f4ebe95beac3f55,0x3f71bf753f180000,0xbf783f22bd49bf0e,0x3f2cbdc9bf043f6d,0xbe16bef13f67bf7b,
0x3f67bef1be163f35,0xbf04bdc93f2cbf7b,0xbd493f22bf783f6d,0x3f18bf753f71bf0e,0xbeacbe953f4ebf80,0xbe793f46bf803f55,0x3f3ebf7f3f5cbec4,0xbf7d3f62bedbbe48,
0x3e2fbf3e3f7fbf55,0xbf1d3f78bf6a3ef1,0xbf393e163efcbf6d,0x3ea13eacbf583f7f,0xbf7a3f67bee6be48,0x3f77bf18bcc93f22,0xbeb83f5cbf7e3f35,0x3f42bf803f51be95,
0xbf7c3f2cbd97bf0e,0x3f4abe79becf3f62,0xbf313f7dbf5f3ec4,0x3f73bf713f093dc9,0x3e603edbbf653f7b,0x3e89bf4e3f80bf46,0x3f6fbf04bdfb3f35,0xbf273d493f13bf75,
0xbef1be483f46bf80,0x3dc93f0ebf753f6d,0x3e95bf553f7fbf35,0xbf223f7bbf623ec4,0x3f62bf7b3f220000,0xbf7f3f55be95bec4,0x3f75bf0ebdc93f35,0xbf463e483ef1bf6d,
0xbf623f7bbf228000,0x3f7fbf553e953ec4,0xbf753f0e3dc9bf35,0x3f46be48bef13f6d,0xbef1be483f46bf80,0x3dc93f0ebf753f6d,0x3e95bf553f7fbf35,0xbf223f7bbf623ec4,
0x3f31bd49bf1d3f7b,0xbee6be793f51bf7f,0x3f7abf18bd973f35,0xbf5f3eac3eb8bf62,0xbecf3f67bf773f0e,0x3f27bf7d3f58be95,0x3e2f3f04bf733f6d,0x3dfbbf3e3f80bf46,
0x3f39bf803f4abe48,0xbf653f78bf13bdc9,0x3e60bf4e3f7fbf35,0xbefc3f71bf6f3ef1,0x3f6abedbbe893f55,0xbf423e163f09bf75,0x3f7cbf5c3ea13ec4,0xbf7e3f2cbcc9bf22,
0xbf7d3f223d49bf35,0x3f71bef1be793f55,0xbf5c3e953edbbf6d,0x3f3ebdc9bf183f7b,0xbf4e3f7fbf2c0000,0x3f67bf753f043e48,0xbf783f62beacbec4,0x3f80bf463e163f0e,
0xbe163f46bf803f35,0x3eacbf623f78bf0e,0xbf043f75bf673ec4,0x3f2cbf7f3f4ebe48,0x3f183dc9bf3e3f80,0xbedbbe953f5cbf7b,0x3e793ef1bf713f6d,0xbd49bf223f7dbf55,
0x3f1dbf7d3f51be48,0xbf313f80bf423dc9,0x3ee6bf713f6abec4,0xbf093f78bf5f3e95,0x3e89bf5c3f7abf0e,0xbeb83f67bf733ef1,0x3d97bf3e3f80bf35,0xbe2f3f4ebf7e3f22,
0xbf4a3e163f13bf7b,0x3f39bd49bf273f7f,0xbf653eac3ecfbf6d,0x3f58be79befc3f75,0xbf773f043e60bf55,0x3f6fbedbbea13f62,0xbf7f3f2c3cc9bf35,0x3f7cbf18bdfb3f46,
0x3f350000bf353f80,0xbf3500003f35bf80,0x3f350000bf353f80,0xbf3500003f35bf80,0x3f350000bf353f80,0xbf3500003f35bf80,0x3f350000bf353f80,0xbf3500003f35bf80,
0xbf353f80bf358000,0x3f35bf803f358000,0xbf353f80bf358000,0x3f35bf803f358000,0xbf353f80bf358000,0x3f35bf803f358000,0xbf353f80bf358000,0x3f35bf803f358000,
0x3e893f78be60bf7b,0x3eb83f71bea1bf75,0x3d973f80bcc9bf80,0x3e2f3f7dbdfbbf7f,0x3f1d3f4ebf13bf55,0x3f313f3ebf27bf46,0x3ee63f67becfbf6d,0x3f093f5cbefcbf62,
0x3f77be79bf7a3e48,0x3f6fbeacbf733e95,0x3f7fbd49bf808000,0x3f7cbe16bf7e3dc9,0x3f4abf18bf513f0e,0x3f39bf2cbf423f22,0x3f65bedbbf6a3ec4,0x3f58bf04bf5f3ef1,
0xbf4ebf223f3e3f35,0xbf67bef13f5c3f0e,0xbf78be953f713ec4,0xbf80bdc93f7d3e48,0xbe16bf7f3d493f80,0xbeacbf753e793f7b,0xbf04bf623edb3f6d,0xbf2cbf463f183f55,
0xbf183f463f2cbf35,0xbedb3f623f04bf55,0xbe793f753eacbf6d,0xbd493f7f3e16bf7b,0xbf7d3dc93f808000,0xbf713e953f78be48,0xbf5c3ef13f67bec4,0xbf3e3f223f4ebf0e,
0x3f6abeacbf773e48,0x3f42bf18bf583ef1,0x3f7c3e79bf73bec4,0x3f7ebd49bf80bdc9,0x3f393f3ebf1dbf55,0x3f653f04bf51bf22,0x3e603f7dbd97bf80,0x3efc3f67beb8bf75,
0xbecfbf713e893f7b,0xbf27bf4e3f093f62,0x3e2fbf78bea13f6d,0xbdfbbf80bcc93f7f,0x3f31bf2cbf4a3f0e,0x3ee6bf5cbf133f46,0x3f7abe16bf7f8000,0x3f5fbedbbf6f3e95,
0xbe95bf7b3dc93f80,0xbf22bf553ef13f6d,0xbf62bf0e3f463f35,0xbf7fbe483f753ec4,0xbf753e483f7f0000,0xbf463f0e3f62bec4,0xbef13f553f22bf35,0xbdc93f7b3e95bf6d,
0xbf753e483f7f8000,0xbf463f0e3f62bec4,0xbef13f553f22bf35,0xbdc93f7b3e95bf6d,0x3e953f7bbdc9bf80,0x3f223f55bef1bf6d,0x3f623f0ebf46bf35,0x3f7f3e48bf75bec4,
0x3f7a3eacbf65bf0e,0x3f77be16bf80bdc9,0x3eb83f78bdfbbf80,0x3f423f3ebf13bf62,0xbe2fbf80bd973f7b,0xbf1dbf5c3ecf3f75,0x3f39bf18bf5f3ec4,0x3ea1bf67bf093f46,
0x3e60bf71bee63f55,0xbe89bf7d3cc93f7f,0x3f6fbe79bf7e8000,0x3f27bf2cbf513ef1,0xbf7c3d493f7f3e48,0xbf4a3f043f6abe95,0xbf31bf4e3efc3f6d,0xbf73bedb3f583f22,
0xbeac3f623f18bf35,0x3e793f7f3d49bf7b,0x3f3e3f46bf04bf6d,0x3f7d3e95bf67bf0e,0xbedbbf753e163f80,0xbf5cbf223f2c3f55,0xbf80bdc93f783ec4,0xbf4e3ef13f71be48,
0x3f713ef1bf4ebf35,0x3f78bdc9bf80be48,0x3f2cbf22bf5c3ec4,0x3e16bf75bedb3f55,0xbf673e953f7d8000,0xbf043f463f3ebf0e,0x3d493f7f3e79bf6d,0x3f183f62beacbf7b,
0xbf7fbe793f6a3f0e,0xbf513edb3f77bdc9,0xbdfbbf80be603f6d,0xbf39bf4e3ee63f75,0x3f73be16bf80be48,0x3f09bf3ebf4a3ef1,0x3efc3f71be2fbf80,0x3f6f3f04bf42bf46,
0xbd973f783ecfbf55,0x3f133f67be89bf7f,0xbf7ebd493f7a3ec4,0xbf313f183f65be95,0xbea1bf7dbcc93f7b,0xbf58bf2c3f1d3f62,0x3f5fbeacbf7c8000,0x3eb8bf5cbf273f22,
0xbf0ebf6d3e483f80,0xbf7bbec43f553f35,0xbf553ec43f7b0000,0xbe483f6d3f0ebf35,0x3f0e3f6dbe48bf80,0x3f7b3ec4bf55bf35,0x3f55bec4bf7b0000,0x3e48bf6dbf0e3f35,
0xbf553ec43f7b8000,0xbe483f6d3f0ebf35,0x3f0e3f6dbe48bf80,0x3f7b3ec4bf55bf35,0x3f55bec4bf7b8000,0x3e48bf6dbf0e3f35,0xbf0ebf6d3e483f80,0xbf7bbec43f553f35,
0x3f27bf18bf6a3e48,0xbe2fbf80be893f62,0x3f1d3f67be60bf80,0x3f803e79bf65bf22,0xbea13f5c3f31bf0e,0x3f093f71bdfbbf7f,0xbf5fbf2c3f133f6d,0xbf6f3e163f7f3e95,
0xbf42bf4e3ecf3f7b,0xbf7cbd493f773ef1,0x3f4abedbbf7a8000,0x3cc9bf78bee63f46,0x3f733f04bf39bf55,0x3f58beacbf7ebdc9,0xbefc3f3e3f51bec4,0x3eb83f7d3d97bf75,
0x3f803e95bf5cbf35,0x3f18bf22bf673e48,0xbeacbf7fbe163f6d,0xbf78bef13f3e3f55,0xbf2cbf623e793f80,0xbf7dbdc93f713f0e,0xbedb3f463f4ebec4,0x3f043f75bd49bf7b,
0x3d49bf75bf043f35,0xbf4ebf463edb3f7b,0xbf713dc93f7d3ec4,0xbe793f623f2cbf0e,0xbf3e3ef13f788000,0x3e163f7f3eacbf55,0x3f673f22bf18bf6d,0x3f5cbe95bf80be48,
0x3f583f3ebee6bf7b,0x3f5fbe79bf80be95,0xbf6a3e163f7e3ec4,0xbd973f713f13bf22,0x3e2fbf67bf273f0e,0xbf4abf4e3eb83f7f,0x3f393f5cbe89bf80,0x3f73bd49bf7abef1,
0x3f09bf2cbf653e48,0xbefcbf78bcc93f75,0x3ecf3f7d3dfbbf6d,0x3f7f3eacbf51bf46,0xbf7cbedb3f423f55,0xbf1d3f183f6fbdc9,0x3f31bf04bf778000,0xbea1bf80be603f62,
0xbf46bf553e953f80,0xbf623e483f7f3ec4,0x3dc93f7b3ef1bf35,0x3f753f0ebf22bf6d,0x3f22bf0ebf750000,0xbef1bf7bbdc93f6d,0xbf7fbe483f623f35,0xbe953f553f46bec4,
0xbf223f0e3f758000,0x3ef13f7b3dc9bf6d,0x3f7f3e48bf62bf35,0x3e95bf55bf463ec4,0xbf46bf553e953f80,0xbf623e483f7f3ec4,0x3dc93f7b3ef1bf35,0x3f753f0ebf22bf6d,
0xbeb8bf80be893f55,0xbf7fbe793f583f46,0x3f513f4ebea1bf80,0x3f4abeacbf80be95,0x3f39bedbbf7ebe48,0xbee6bf7dbe2f3f62,0xbe603f5c3f42bec4,0x3f5f3f3ebecfbf7f,
0xbf6f3d493f773f0e,0x3d973f783f09bf22,0x3f13bf18bf738000,0xbf1dbf713cc93f75,0xbf31bf673dfb3f7b,0xbf653e163f7c3ef1,0x3f7a3f04bf27bf6d,0x3efcbf2cbf6a3dc9,
0xbe79bf7fbedb3f35,0xbf80be953f4e3f55,0xbe163f623f3ebec4,0x3f713f22bf04bf7b,0xbf5cbf463eac3f80,0xbf2c3ef13f7d3e48,0x3f183f753d49bf6d,0x3f67bdc9bf78bf0e,
0xbf78bdc93f673f35,0x3d493f753f18bf0e,0x3f7d3ef1bf2cbf6d,0x3eacbf46bf5c3e48,0xbf043f223f718000,0x3f3e3f62be16bf7b,0x3f4ebe95bf80bec4,0xbedbbf7fbe793f55,
0xbefcbf7dbe603f55,0xbf6a3d493f733f22,0x3f273f713cc9bf6d,0x3f51be79bf7ebef1,0xbf4abf5c3e2f3f7b,0xbf313edb3f7f3e95,0x3f653f3ebeb8bf80,0x3f09bf18bf77bdc9,
0xbf5f3e163f7a3f0e,0x3ecf3f803ea1bf46,0x3f42beacbf80bec4,0xbf13bf78bdfb3f62,0xbf1d3f043f7c3e48,0x3f393f67bd97bf75,0x3ee6bf2cbf6f8000,0xbf58bf4e3e893f7f,
0xbf6dbf353ec43f80,0xbec43f353f6d0000,0x3f6d3f35bec4bf80,0x3ec4bf35bf6d0000,0xbf6dbf353ec43f80,0xbec43f353f6d0000,0x3f6d3f35bec4bf80,0x3ec4bf35bf6d0000,
0xbec43f353f6d8000,0x3f6d3f35bec4bf80,0x3ec4bf35bf6d8000,0xbf6dbf353ec43f80,0xbec43f353f6d8000,0x3f6d3f35bec4bf80,0x3ec4bf35bf6d8000,0xbf6dbf353ec43f80,
0xbf7ebf043f133f7b,0xbcc93f673f42be95,0x3f733f2cbecfbf80,0x3e60bf4ebf5f3dc9,0xbf77be163f583f55,0x3eb83f803ee6bf22,0x3f7f3eacbf39bf6d,0xbe2fbf78bf1d3ef1,
0xbdfb3f5c3f51be48,0x3f803edbbf27bf75,0x3ea1bf3ebf6a8000,0xbf7abf183efc3f7f,0x3e893f7d3f09bf0e,0x3f6f3d49bf65bf46,0xbd97bf71bf313ec4,0xbf7cbe793f4a3f62,
0xbf5c3dc93f713f35,0x3f2c3f753e16bf55,0x3f18bef1bf80bec4,0xbf67bf463e793f7b,0xbf78bf223edb3f80,0xbd493f623f4ebe48,0x3f7d3e95bf3ebf6d,0xbeacbf7fbf043f0e,
0x3f043f7f3eacbf35,0x3f3ebe95bf7dbf0e,0xbf4ebf623d493f6d,0xbedb3f223f783e48,0xbe793f463f678000,0x3f803ef1bf18bf7b,0xbe16bf75bf2c3ec4,0xbf71bdc93f5c3f55,
0x3cc93f673f4abe48,0x3f733e16bf51bf62,0x3f09bf04bf7fbec4,0xbf77bf2c3eb83f7f,0xbf6abd493f5f3f55,0x3f273f783e60bf46,0x3f7c3f18bee6bf80,0xbdfbbf71bf393e95,
0x3f803edbbf1dbf7b,0xbea1bf7dbf133ef1,0xbf58bf5c3d973f6d,0xbe893f3e3f6f3dc9,0x3ecf3f803efcbf0e,0x3f42be79bf7abf22,0x3e2fbf4ebf658000,0xbf7ebeac3f313f75,
0xbf7fbf0e3ef13f80,0x3e953f7b3f22bec4,0x3f46be48bf75bf35,0xbf62bf553dc93f6d,0xbdc93f553f620000,0x3f753e48bf46bf6d,0xbf22bf7bbe953f35,0xbef13f0e3f7f3ec4,
0xbdc93f553f628000,0x3f753e48bf46bf6d,0xbf22bf7bbe953f35,0xbef13f0e3f7f3ec4,0x3f7f3f0ebef1bf80,0xbe95bf7bbf223ec4,0xbf463e483f753f35,0x3f623f55bdc9bf6d,
0xbf133edb3f7f3f0e,0x3f7e3f18becfbf7f,0x3f803f04befcbf80,0xbee6bf80bf093ef1,0x3f7a3f2cbea1bf7b,0xbe89bf78bf313e95,0xbeb8bf7dbf1d3ec4,0xbf273eac3f7c3f22,
0x3f513f673d97bf55,0x3dfbbf4ebf6abdc9,0x3cc9bf5cbf5f8000,0xbf65bd493f583f62,0x3e60bf3ebf73be48,0xbf77be793f393f75,0xbf6fbe163f4a3f6d,0x3f423f713e2fbf46,
0x3f3e3f753e79bf35,0x3e16bf46bf71be48,0xbf67bdc93f4e3f6d,0x3f5c3f623d49bf55,0xbf80bef13f043f80,0x3f183f7f3edbbf0e,0x3eacbf22bf7dbec4,0xbf78be953f2c3f7b,
0x3f2cbe95bf78bf35,0xbf7dbf223eac3f7b,0x3edb3f7f3f18bec4,0x3f04bef1bf80bf0e,0x3d493f623f5c8000,0x3f4ebdc9bf67bf55,0xbf71bf463e163f6d,0x3e793f753f3ebe48,
0x3ee6bf04bf80bf0e,0xbf7abeac3f1d3f7f,0xbf77bf3e3e2f3f6d,0x3ecf3f7d3f27be95,0xbd973f4e3f6f3e48,0x3f51bd49bf5fbf62,0x3f7e3edbbf09bf80,0xbf39bf78bea13f22,
0xbf65bf5cbcc93f55,0x3e603f713f4abdc9,0xbe893f2c3f7c3ec4,0x3f6a3e16bf42bf75,0x3f7f3f18beb8bf7b,0xbf13bf80befc3ef1,0xbdfbbf67bf588000,0xbf313e793f733f46,
0xbf7bbec43f0e3f80,0x3f553f6d3e48bf35,0xbe48bf6dbf550000,0xbf0e3ec43f7b3f35,0x3f7b3ec4bf0ebf80,0xbf55bf6dbe483f35,0x3e483f6d3f550000,0x3f0ebec4bf7bbf35,
0x3e483f6d3f558000,0x3f0ebec4bf7bbf35,0xbf7bbec43f0e3f80,0x3f553f6d3e48bf35,0xbe48bf6dbf558000,0xbf0e3ec43f7b3f35,0x3f7b3ec4bf0ebf80,0xbf55bf6dbe483f35,
0x3ee63f7d3f31be48,0x3e60bf2cbf7ebef1,0x3f773eacbf13bf80,0xbf6abf5cbd973f46,0xbf42bf78beb83f0e,0x3e2f3f673f5f3dc9,0xbf4a3d493f583f6d,0x3f803f18bea1bf75,
0x3f653e16bf39bf7b,0xbf7abf3e3dfb3f62,0xbe89bf71bf518000,0xbecf3f043f7f3f22,0xbf273e793f6f3f55,0x3f7c3edbbefcbf7f,0x3f1d3f803f09bec4,0x3cc9bf4ebf73be95,
0x3edbbef1bf7dbf35,0xbf5cbdc93f3e3f7b,0x3f803f22be79bf6d,0xbf4ebf75beac3f0e,0xbf71be953f183f80,0x3f783f46bd49bf55,0xbf2cbf7fbf043ec4,0x3e163f623f673e48,
0xbf67bf62be163f35,0x3f043f7f3f2cbe48,0x3d49bf46bf78bec4,0xbf183e953f713f55,0x3eac3f753f4e8000,0x3e79bf22bf80bf0e,0xbf3e3dc93f5c3f6d,0x3f7d3ef1bedbbf7b,
0xbf51bd493f423f7b,0x3f7e3f04beb8bf75,0x3cc93f4e3f773ec4,0x3ee6bedbbf7abf46,0x3f583f713ea1bf0e,0xbefcbf7dbf393dc9,0x3f6a3e79bf1dbf80,0xbf7fbf2c3e2f3f62,
0x3f133f803f27be48,0xbdfbbf5cbf6fbe95,0x3f803f18be89bf6d,0xbf65bf67be603f22,0x3f09beacbf73bf55,0xbf5fbe163f313f7f,0xbecfbf78bf4a8000,0xbd973f3e3f7c3ef1,
0xbf62be483f223f80,0x3f7f3f0ebe95bf6d,0xbf75bf55bdc93f35,0x3f463f7b3ef1bec4,0xbef1bf7bbf460000,0x3dc93f553f753ec4,0x3e95bf0ebf7fbf35,0xbf223e483f623f6d,
0x3ef13f7b3f468000,0xbdc9bf55bf75bec4,0xbe953f0e3f7f3f35,0x3f22be48bf62bf6d,0xbf62be483f223f80,0x3f7f3f0ebe95bf6d,0xbf75bf55bdc93f35,0x3f463f7b3ef1bec4,
0x3f803f2cbdfbbf55,0xbf73bf5cbe2f3f22,0x3f583e16bf27bf80,0xbf77bedb3ecf3f75,0x3eb83f713f5f3e48,0xbd97bf4ebf7abef1,0x3f513f783ee6bec4,0xbf1dbf80bf313dc9,
0x3cc9bf3ebf7ebf0e,0xbea13f043f7c3f46,0xbf09bf7dbf428000,0x3e893f673f6a3e95,0x3f6f3eacbefcbf7b,0xbf7fbf183e603f62,0x3f13be79bf65bf6d,0xbf4abd493f393f7f,
0xbf7dbf46bd493f35,0x3f713f623e79bf0e,0xbf5cbf75bedb3ec4,0x3f3e3f7f3f18be48,0xbf4ebdc93f2c3f80,0x3f673e95bf04bf7b,0xbf78bef13eac3f6d,0x3f803f22be16bf55,
0xbe163f223f803f35,0x3eacbef1bf78bf55,0xbf043e953f673f6d,0x3f2cbdc9bf4ebf7b,0x3f183f7f3f3e8000,0xbedbbf75bf5cbe48,0x3e793f623f713ec4,0xbd49bf46bf7dbf0e,
0x3f7e3f18be2fbf55,0xbf80bf2c3d973f46,0x3f733edbbeb8bf6d,0xbf7abf043e893f62,0x3f5f3e79bf09bf7b,0xbf6abeac3ee63f75,0x3f423d49bf31bf80,0xbf51be163f1d3f7f,
0xbdfbbf4ebf7cbf0e,0x3cc93f3e3f7f3f22,0xbea1bf67bf6fbec4,0x3e603f5c3f773ef1,0xbefcbf78bf58be48,0x3ecf3f713f653e95,0xbf27bf80bf398000,0x3f133f7d3f4a3dc9,
0x3f350000bf353f80,0xbf3500003f35bf80,0x3f350000bf353f80,0xbf3500003f35bf80,0x3f350000bf353f80,0xbf3500003f35bf80,0x3f350000bf353f80,0xbf3500003f35bf80,
0xbf353f80bf358000,0x3f35bf803f358000,0xbf353f80bf358000,0x3f35bf803f358000,0xbf353f80bf358000,0x3f35bf803f358000,0xbf353f80bf358000,0x3f35bf803f358000,
0x3f5f3f04bf58bf0e,0x3f6a3edbbf65bef1,0x3f423f2cbf39bf35,0x3f513f18bf4abf22,0x3f7e3e16bf7cbe48,0x3f803d49bf7fbdc9,0x3f733eacbf6fbec4,0x3f7a3e79bf77be95,
0x3efcbf5cbf093f55,0x3ecfbf67bee63f62,0x3f27bf3ebf313f35,0x3f13bf4ebf1d3f46,0x3dfbbf7dbe2f3f7b,0x3cc9bf80bd973f7f,0x3ea1bf71beb83f6d,0x3e60bf78be893f75,
0xbf183f463f2cbf35,0xbedb3f623f04bf55,0xbe793f753eacbf6d,0xbd493f7f3e16bf7b,0xbf7d3dc93f800000,0xbf713e953f78be48,0xbf5c3ef13f67bec4,0xbf3e3f223f4ebf0e,
0x3f4e3f22bf3ebf35,0x3f673ef1bf5cbf0e,0x3f783e95bf71bec4,0x3f803dc9bf7dbe48,0x3e163f7fbd49bf80,0x3eac3f75be79bf7b,0x3f043f62bedbbf6d,0x3f2c3f46bf18bf55,
0xbf6fbedb3f5f3f0e,0xbf7fbe163f7a3e95,0xbf13bf5c3ee63f6d,0xbf4abf2c3f313f46,0xbcc9bf80bdfb3f7b,0xbea1bf783e2f3f7f,0x3f09bf4ebf273f35,0x3e89bf71becf3f62,
0xbeb83f673efcbf55,0xbd973f7d3e60bf75,0xbf513f043f65bec4,0xbf1d3f3e3f39bf22,0xbf80bd493f7e3e48,0xbf733e793f7cbdc9,0xbf58bf183f423f35,0xbf77beac3f6a3ef1,
0x3e953f7bbdc9bf80,0x3f223f55bef1bf6d,0x3f623f0ebf46bf35,0x3f7f3e48bf75bec4,0x3f75be48bf7f0000,0x3f46bf0ebf623ec4,0x3ef1bf55bf223f35,0x3dc9bf7bbe953f6d,
0x3f75be48bf7f8000,0x3f46bf0ebf623ec4,0x3ef1bf55bf223f35,0x3dc9bf7bbe953f6d,0xbe95bf7b3dc93f80,0xbf22bf553ef13f6d,0xbf62bf0e3f463f35,0xbf7fbe483f753ec4,
0xbf583edb3f73be48,0xbefc3f4e3f31bf22,0xbf6abf043f4a3f35,0xbf7fbd493f7c3e95,0x3f513f2cbf27bf55,0x3f7e3e79bf6fbef1,0xbcc93f7d3e89bf6d,0x3ee63f71be60bf7f,
0x3f093f67bea1bf7b,0x3f5f3f18bf39bf46,0xbecf3f5c3f1dbf35,0x3d973f803e2fbf75,0x3f13bf3ebf423f0e,0x3dfbbf78beb83f62,0x3f803e16bf77bec4,0x3f65beacbf7a3dc9,
0xbf71bef13f4e3f35,0xbf783dc93f803e48,0xbf2c3f223f5cbec4,0xbe163f753edbbf55,0x3f67be95bf7d0000,0x3f04bf46bf3e3f0e,0xbd49bf7fbe793f6d,0xbf18bf623eac3f7b,
0xbeac3f623f18bf35,0x3e793f7f3d49bf7b,0x3f3e3f46bf04bf6d,0x3f7d3e95bf67bf0e,0xbedbbf753e163f80,0xbf5cbf223f2c3f55,0xbf80bdc93f783ec4,0xbf4e3ef13f71be48,
0xbf27bf5c3eb83f7b,0xbf7cbeac3f5f3f22,0x3f1dbf2cbf583ec4,0xbcc9bf7dbea13f62,0x3f653f18bf31bf55,0x3f7abd49bf7ebe95,0xbe893f673f13bf35,0x3ecf3f78bd97bf7f,
0xbf423f043f6fbe48,0xbe2f3f713efcbf46,0xbf4abf3e3f093f6d,0xbf80be163f733ef1,0x3ee6bf4ebf393f0e,0xbe60bf80bdfb3f75,0x3f773edbbf51bf35,0x3f6abe79bf7fbdc9,
0xbf0ebf6d3e483f80,0xbf7bbec43f553f35,0xbf553ec43f7b0000,0xbe483f6d3f0ebf35,0x3f0e3f6dbe48bf80,0x3f7b3ec4bf55bf35,0x3f55bec4bf7b0000,0x3e48bf6dbf0e3f35,
0xbf553ec43f7b8000,0xbe483f6d3f0ebf35,0x3f0e3f6dbe48bf80,0x3f7b3ec4bf55bf35,0x3f55bec4bf7b8000,0x3e48bf6dbf0e3f35,0xbf0ebf6d3e483f80,0xbf7bbec43f553f35,
0xbd97bf7dbeb83f55,0xbf51bf3e3efc3f75,0x3f7e3eacbf58bf35,0x3f39bf04bf733dc9,0x3ee63f78bcc9bf7b,0x3f7a3edbbf4abf46,0xbf773d493f7c3ec4,0xbecf3f4e3f42bef1,
0xbf7fbe163f6f3f0e,0xbf133f2c3f5fbe95,0x3dfbbf71bf093f35,0xbf31bf5c3ea13f7f,0x3f65be79bf80be48,0x3e60bf67bf1d3f22,0x3e893f803e2fbf6d,0x3f6a3f18bf27bf62,
0x3d49bf75bf043f35,0xbf4ebf463edb3f7b,0xbf713dc93f7d3ec4,0xbe793f623f2cbf0e,0xbf3e3ef13f780000,0x3e163f7f3eacbf55,0x3f673f22bf18bf6d,0x3f5cbe95bf80be48,
0xbf80be953f5c3f35,0xbf183f223f67be48,0x3eac3f7f3e16bf6d,0x3f783ef1bf3ebf55,0x3f2c3f62be79bf80,0x3f7d3dc9bf71bf0e,0x3edbbf46bf4e3ec4,0xbf04bf753d493f7b,
0xbe60bf80bea13f55,0xbf77bf043f313f62,0x3f6f3f18bf1dbf6d,0x3f42bedbbf7cbdc9,0xbf513eac3f7f3e48,0x3dfb3f7d3ecfbf46,0xbcc9bf78befc3f35,0xbf65bf2c3f093f75,
0xbf7abd493f733f0e,0xbe893f5c3f39bef1,0x3eb8bf4ebf4a3ec4,0xbf27bf673e2f3f7f,0x3f133f71bd97bf7b,0x3f7e3e16bf6abf22,0xbf80be793f5f3f35,0xbee63f3e3f58be95,
0x3f463f55be95bf80,0x3f62be48bf7fbec4,0xbdc9bf7bbef13f35,0xbf75bf0e3f223f6d,0xbf223f0e3f750000,0x3ef13f7b3dc9bf6d,0x3f7f3e48bf62bf35,0x3e95bf55bf463ec4,
0x3f22bf0ebf758000,0xbef1bf7bbdc93f6d,0xbf7fbe483f623f35,0xbe953f553f46bec4,0x3f463f55be95bf80,0x3f62be48bf7fbec4,0xbdc9bf7bbef13f35,0xbf75bf0e3f223f6d,
0x3f6a3f2cbefcbf7b,0x3f27bf04bf7abdc9,0xbf7cbe163f653f35,0xbdfb3f673f31bef1,0xbcc93f713f1dbf0e,0x3f733f18bf13bf75,0xbf09bf78bd973f6d,0xbf77bd493f6f3f22,
0x3ecfbf3ebf5f3e48,0xbf42bf5c3e603f7f,0x3e2f3f7d3ee6bf35,0x3f7e3edbbf39bf62,0x3f803eacbf4abf55,0x3ea1bf4ebf513e95,0xbf583e793f7f3ec4,0x3e893f803eb8bf46,
0x3f783dc9bf67bf35,0xbd49bf75bf183f0e,0xbf7dbef13f2c3f6d,0xbeac3f463f5cbe48,0x3f04bf22bf710000,0xbf3ebf623e163f7b,0xbf4e3e953f803ec4,0x3edb3f7f3e79bf55,
0xbe79bf7fbedb3f35,0xbf80be953f4e3f55,0xbe163f623f3ebec4,0x3f713f22bf04bf7b,0xbf5cbf463eac3f80,0xbf2c3ef13f7d3e48,0x3f183f753d49bf6d,0x3f67bdc9bf78bf0e,
0x3e89bf4ebf583e48,0xbf6fbf2c3ee63f7f,0xbd973f673f39bec4,0x3f7c3f04bf1dbf75,0xbdfbbf78bf133f0e,0xbf80beac3f423f62,0x3ea13f803ecfbf35,0x3f7a3e16bf5fbf46,
0xbf77bf183f093f7b,0xbeb83f3e3f65bdc9,0x3f7f3edbbf31bf6d,0x3e2fbf5cbf4a3e95,0xbf7ebe793f513f55,0x3cc93f713f27bef1,0x3f733d49bf6abf35,0xbe60bf7dbefc3f22,
0xbf6dbf353ec43f80,0xbec43f353f6d0000,0x3f6d3f35bec4bf80,0x3ec4bf35bf6d0000,0xbf6dbf353ec43f80,0xbec43f353f6d0000,0x3f6d3f35bec4bf80,0x3ec4bf35bf6d0000,
0xbec43f353f6d8000,0x3f6d3f35bec4bf80,0x3ec4bf35bf6d8000,0xbf6dbf353ec43f80,0xbec43f353f6d8000,0x3f6d3f35bec4bf80,0x3ec4bf35bf6d8000,0xbf6dbf353ec43f80,
0xbf4a3e793f7c3f0e,0x3f313f713d97bf62,0x3f65bd49bf6fbf35,0xbf09bf7dbe893f46,0xbefc3f183f7a3e48,0x3f6a3f3ebea1bf7f,0x3f27bedbbf80bec4,0xbf51bf5c3dfb3f75,
0x3f1d3f783e2fbf55,0x3f39beacbf7fbef1,0xbee6bf80beb83f35,0xbf583e163f773f22,0x3f5f3f4ebe60bf7b,0x3ecfbf2cbf73bdc9,0xbf42bf673cc93f6d,0xbf133f043f7e3e95,
0x3f043f7f3eacbf35,0x3f3ebe95bf7dbf0e,0xbf4ebf623d493f6d,0xbedb3f223f783e48,0xbe793f463f670000,0x3f803ef1bf18bf7b,0xbe16bf75bf2c3ec4,0xbf71bdc93f5c3f55,
0x3f5cbdc9bf71bf35,0xbf2cbf75be163f55,0xbf183ef13f803ec4,0x3f673f46be79bf7b,0x3f783f22bedbbf80,0x3d49bf62bf4e3e48,0xbf7dbe953f3e3f6d,0x3eac3f7f3f04bf0e,
0x3f31beacbf7ebf0e,0xbf65bf4e3e2f3f75,0xbf7abe793f423f6d,0x3efc3f803ecfbf22,0x3f6f3f3ebe89bf7b,0x3d97bf5cbf583dc9,0xbf13bf7dbea13f35,0xbf1d3edb3f803ef1,
0xbf39bf71bdfb3f55,0xbee63f183f7c3e95,0x3e603f783f27bec4,0x3f5fbd49bf6abf46,0x3eb8bf2cbf77be48,0xbf7fbf043f093f7f,0xbf513e163f733f35,0x3f4a3f673cc9bf62,
0x3f7f3f0ebef1bf80,0xbe95bf7bbf223ec4,0xbf463e483f753f35,0x3f623f55bdc9bf6d,0x3dc9bf55bf620000,0xbf75be483f463f6d,0x3f223f7b3e95bf35,0x3ef1bf0ebf7fbec4,
0x3dc9bf55bf628000,0xbf75be483f463f6d,0x3f223f7b3e95bf35,0x3ef1bf0ebf7fbec4,0xbf7fbf0e3ef13f80,0x3e953f7b3f22bec4,0x3f46be48bf75bf35,0xbf62bf553dc93f6d,
0xbe2fbf71bf423e48,0xbf4a3e163f6f3f46,0xbf393e793f773f35,0x3f733f3ebe60bf75,0xbf583d493f653f55,0x3f5f3f5cbcc9bf62,0x3f6a3f4ebdfbbf6d,0xbd97bf67bf513dc9,
0xbf7cbeac3f273f7b,0x3f1d3f7d3eb8bf22,0x3f313f783e89bf35,0x3ea1bf2cbf7abe95,0x3f093f803ee6bf0e,0x3efcbf04bf80bef1,0x3ecfbf18bf7ebec4,0xbf7fbedb3f133f7f,
0xbf2c3e953f783f35,0x3f7d3f22beacbf7b,0xbedbbf7fbf183ec4,0xbf043ef13f803f0e,0xbd49bf62bf5c0000,0xbf4e3dc93f673f55,0x3f713f46be16bf6d,0xbe79bf75bf3e3e48,
0x3f3e3f753e79bf35,0x3e16bf46bf71be48,0xbf67bdc93f4e3f6d,0x3f5c3f623d49bf55,0xbf80bef13f043f80,0x3f183f7f3edbbf0e,0x3eacbf22bf7dbec4,0xbf78be953f2c3f7b,
0x3f733e79bf31bf7b,0xbf58bf67bdfb3f46,0xbefcbf80bf133ec4,0xbeb83f183f7f3ef1,0xbf423e163f6a3f55,0x3f7c3f2cbe89bf75,0x3f4a3f713e60bf35,0xbcc9bf5cbf65bdc9,
0xbea1bf78bf393e48,0xbf093edb3f7e3f22,0xbf5fbd493f513f6d,0x3f6f3f4ebd97bf62,0x3f273f7d3ecfbf0e,0x3e2fbf3ebf77be95,0x3f1dbeacbf7abf35,0xbf80bf043ee63f7f,
0xbf7bbec43f0e3f80,0x3f553f6d3e48bf35,0xbe48bf6dbf550000,0xbf0e3ec43f7b3f35,0x3f7b3ec4bf0ebf80,0xbf55bf6dbe483f35,0x3e483f6d3f550000,0x3f0ebec4bf7bbf35,
0x3e483f6d3f558000,0x3f0ebec4bf7bbf35,0xbf7bbec43f0e3f80,0x3f553f6d3e48bf35,0xbe48bf6dbf558000,0xbf0e3ec43f7b3f35,0x3f7b3ec4bf0ebf80,0xbf55bf6dbe483f35,
0x3f733f4ebcc9bf55,0xbf09bf80bf1d3e95,0x3efcbedbbf7cbf35,0xbf6fbe793f273f7f,0xbf7fbf043ecf3f7b,0x3f513f713e89bf22,0xbdfb3f3e3f7a3ec4,0x3f39be16bf65bf62,
0x3ea1bf18bf80bf0e,0xbf58bd493f4a3f75,0xbf5fbf67be2f3f35,0x3eb83f783f42bdc9,0x3d973f5c3f6a3e48,0x3f13beacbf77bf46,0x3f7e3f2cbe60bf6d,0xbf31bf7dbee63ef1,
0xbf67bf62be163f35,0x3f043f7f3f2cbe48,0x3d49bf46bf78bec4,0xbf183e953f713f55,0x3eac3f753f4e0000,0x3e79bf22bf80bf0e,0xbf3e3dc93f5c3f6d,0x3f7d3ef1bedbbf7b,
0xbedb3ef13f7d3f35,0x3f5c3dc9bf3ebf7b,0xbf80bf223e793f6d,0x3f4e3f753eacbf0e,0x3f713e95bf18bf80,0xbf78bf463d493f55,0x3f2c3f7f3f04bec4,0xbe16bf62bf67be48,
0x3f7c3f3ebd97bf55,0xbf4abf78becf3ef1,0x3f31be16bf5fbf6d,0xbf73beac3f093f7f,0xbe60bf67bf65be48,0xbe893f183f803f22,0xbf6fbf5cbdfb3f35,0x3f273f803f13be95,
0x3e2fbf2cbf7fbf0e,0xbf1d3e793f6a3f62,0xbf39bf7dbefc3ec4,0x3ea13f713f583dc9,0xbf7abedb3ee63f7b,0x3f773f4e3cc9bf46,0xbeb83f043f7e3f35,0x3f42bd49bf51bf75,
0x3f623e48bf22bf80,0xbf7fbf0e3e953f6d,0x3f753f553dc9bf35,0xbf46bf7bbef13ec4,0x3ef13f7b3f460000,0xbdc9bf55bf75bec4,0xbe953f0e3f7f3f35,0x3f22be48bf62bf6d,
0xbef1bf7bbf468000,0x3dc93f553f753ec4,0x3e95bf0ebf7fbf35,0xbf223e483f623f6d,0x3f623e48bf22bf80,0xbf7fbf0e3e953f6d,0x3f753f553dc9bf35,0xbf46bf7bbef13ec4,
0xbf393d493f4a3f7b,0x3f653e79bf13bf7f,0xbe603f183f7f3f35,0x3efcbeacbf6fbf62,0xbf6abf67be893f0e,0x3f423f7d3f09be95,0xbf7cbf043ea13f6d,0x3f7e3f3ebcc9bf46,
0x3f313f803f1dbe48,0xbee6bf78bf51bdc9,0x3f7a3f4e3d97bf35,0xbf5fbf71beb83ef1,0xbecf3edb3f773f55,0x3f27be16bf58bf75,0x3e2f3f5c3f733ec4,0x3dfbbf2cbf80bf22,
0x3e16bf22bf80bf35,0xbeac3ef13f783f55,0x3f04be95bf67bf6d,0xbf2c3dc93f4e3f7b,0xbf18bf7fbf3e0000,0x3edb3f753f5c3e48,0xbe79bf62bf71bec4,0x3d493f463f7d3f0e,
0xbf7dbf46bd493f35,0x3f713f623e79bf0e,0xbf5cbf75bedb3ec4,0x3f3e3f7f3f18be48,0xbf4ebdc93f2c3f80,0x3f673e95bf04bf7b,0xbf78bef13eac3f6d,0x3f803f22be16bf55,
0x3f4a3f7d3f13be48,0xbf39bf80bf273dc9,0x3f653f713ecfbec4,0xbf58bf78befc3e95,0x3f773f5c3e60bf0e,0xbf6fbf67bea13ef1,0x3f7f3f3e3cc9bf35,0xbf7cbf4ebdfb3f22,
0x3f1dbe16bf51bf7b,0xbf313d493f423f7f,0x3ee6beacbf6abf6d,0xbf093e793f5f3f75,0x3e89bf04bf7abf55,0xbeb83edb3f733f62,0x3d97bf2cbf80bf35,0xbe2f3f183f7e3f46,
0x3f003f003f003f00,0x3f003f003f003f00,0x3f003f003f003f00,0x3f003f003f003f00,0x3f003f003f003f00,0x3f003f003f003f00,0x3f003f003f003f00,0x3f003f003f003f00,
0xbf003f00bf003f00,0xbf003f00bf003f00,0xbf003f00bf003f00,0xbf003f00bf003f00,0xbf003f00bf003f00,0xbf003f00bf003f00,0xbf003f00bf003f00,0xbf003f00bf003f00,
0x3e893e793e603e48,0x3eb83eac3ea13e95,0x3d973d493cc90000,0x3e2f3e163dfb3dc9,0x3f1d3f183f133f0e,0x3f313f2c3f273f22,0x3ee63edb3ecf3ec4,0x3f093f043efc3ef1,
0x3f773f783f7a3f7b,0x3f6f3f713f733f75,0x3f7f3f803f803f80,0x3f7c3f7d3f7e3f7f,0x3f4a3f4e3f513f55,0x3f393f3e3f423f46,0x3f653f673f6a3f6d,0x3f583f5c3f5f3f62,
0xbf18bf22bf2cbf35,0xbedbbef1bf04bf0e,0xbe79be95beacbec4,0xbd49bdc9be16be48,0xbf7dbf7fbf80bf80,0xbf71bf75bf78bf7b,0xbf5cbf62bf67bf6d,0xbf3ebf46bf4ebf55,
0x3f4e3f463f3e3f35,0x3f673f623f5c3f55,0x3f783f753f713f6d,0x3f803f7f3f7d3f7b,0x3e163dc93d498000,0x3eac3e953e793e48,0x3f043ef13edb3ec4,0x3f2c3f223f183f0e,
0xbf6abf71bf77bf7b,0xbf42bf4ebf58bf62,0xbf7cbf78bf73bf6d,0xbf7ebf80bf80bf7f,0xbf39bf2cbf1dbf0e,0xbf65bf5cbf51bf46,0xbe60be16bd970000,0xbefcbedbbeb8be95,
0x3ecf3eac3e893e48,0x3f273f183f093ef1,0xbe2fbe79bea1bec4,0x3dfb3d49bcc9bdc9,0xbf31bf3ebf4abf55,0xbee6bf04bf13bf22,0xbf7abf7dbf7fbf80,0xbf5fbf67bf6fbf75,
0x3f753f7b3f7f3f80,0x3f463f553f623f6d,0x3ef13f0e3f223f35,0x3dc93e483e953ec4,0xbe95be48bdc90000,0xbf22bf0ebef1bec4,0xbf62bf55bf46bf35,0xbf7fbf7bbf75bf6d,
0xbe95be48bdc98000,0xbf22bf0ebef1bec4,0xbf62bf55bf46bf35,0xbf7fbf7bbf75bf6d,0xbf75bf7bbf7fbf80,0xbf46bf55bf62bf6d,0xbef1bf0ebf22bf35,0xbdc9be48be95bec4,
0x3f7a3f713f653f55,0x3f773f7d3f803f7f,0x3eb83e793dfb0000,0x3f423f2c3f133ef1,0xbe2fbd493d973e48,0xbf1dbf04becfbe95,0x3f393f4e3f5f3f6d,0x3ea13edb3f093f22,
0x3e603eac3ee63f0e,0xbe89be16bcc93dc9,0x3f6f3f783f7e3f80,0x3f273f3e3f513f62,0xbf7cbf80bf7fbf7b,0xbf4abf5cbf6abf75,0xbf31bf18befcbec4,0xbf73bf67bf58bf46,
0x3f713f623f4e3f35,0x3f783f7f3f803f7b,0x3f2c3f463f5c3f6d,0x3e163e953edb3f0e,0xbf67bf75bf7dbf80,0xbf04bf22bf3ebf55,0x3d49bdc9be79bec4,0x3f183ef13eac3e48,
0x3eac3ef13f183f35,0xbe79bdc93d493e48,0xbf3ebf22bf04bec4,0xbf7dbf75bf67bf55,0x3edb3e953e168000,0x3f5c3f463f2c3f0e,0x3f803f7f3f783f6d,0x3f4e3f623f713f7b,
0x3f7f3f783f6a3f55,0x3f513f673f773f7f,0x3dfbbd49be60bec4,0x3f393f183ee63e95,0xbf73bf7dbf80bf7b,0xbf09bf2cbf4abf62,0xbefcbeacbe2f0000,0xbf6fbf5cbf42bf22,
0x3d973e793ecf3f0e,0xbf13bedbbe89bdc9,0x3f7e3f803f7a3f6d,0x3f313f4e3f653f75,0x3ea13e16bcc9be48,0x3f583f3e3f1d3ef1,0xbf5fbf71bf7cbf80,0xbeb8bf04bf27bf46,
0x3f553f6d3f7b3f80,0x3e483ec43f0e3f35,0xbf0ebec4be480000,0xbf7bbf6dbf55bf35,0xbf55bf6dbf7bbf80,0xbe48bec4bf0ebf35,0x3f0e3ec43e480000,0x3f7b3f6d3f553f35,
0xbf0ebec4be488000,0xbf7bbf6dbf55bf35,0xbf55bf6dbf7bbf80,0xbe48bec4bf0ebf35,0x3f0e3ec43e488000,0x3f7b3f6d3f553f35,0x3f553f6d3f7b3f80,0x3e483ec43f0e3f35,
0x3f273f4e3f6a3f7b,0xbe2f3d493e893ef1,0x3f1d3edb3e600000,0x3f803f783f653f46,0xbea1bf04bf31bf55,0x3f093eac3dfbbdc9,0xbf5fbf3ebf13bec4,0xbf6fbf7dbf7fbf75,
0xbf42bf18becfbe48,0xbf7cbf80bf77bf62,0x3f4a3f673f7a3f80,0x3cc93e793ee63f22,0x3f733f5c3f393f0e,0x3f583f713f7e3f7f,0xbefcbf2cbf51bf6d,0x3eb83e16bd97be95,
0x3d493e953f043f35,0xbf4ebf22bedbbe48,0xbf71bf7fbf7dbf6d,0xbe79bef1bf2cbf55,0xbf3ebf62bf78bf80,0x3e16bdc9beacbf0e,0x3f673f463f183ec4,0x3f5c3f753f803f7b,
0xbf80bf75bf5cbf35,0xbf18bf46bf67bf7b,0x3eac3dc9be16bec4,0x3f783f623f3e3f0e,0x3f2c3ef13e798000,0x3f7d3f7f3f713f55,0x3edb3f223f4e3f6d,0xbf04be95bd493e48,
0xbf58bf2cbee6be48,0xbf5fbf78bf80bf75,0x3f6a3f7d3f7e3f6d,0x3d973eac3f133f46,0xbe2fbedbbf27bf55,0x3f4a3f183eb83dc9,0xbf39bf04be890000,0xbf73bf80bf7abf62,
0xbf09bf3ebf65bf7b,0x3efc3e79bcc9be95,0xbecfbe163dfb3ec4,0xbf7fbf71bf51bf22,0x3f7c3f673f423f0e,0x3f1d3f4e3f6f3f7f,0xbf31bf5cbf77bf80,0x3ea13d49be60bef1,
0x3f223f553f753f80,0xbef1be483dc93ec4,0xbf7fbf7bbf62bf35,0xbe95bf0ebf46bf6d,0x3f463f0e3e950000,0x3f623f7b3f7f3f6d,0xbdc93e483ef13f35,0xbf75bf55bf22bec4,
0xbf46bf0ebe958000,0xbf62bf7bbf7fbf6d,0x3dc9be48bef1bf35,0x3f753f553f223ec4,0x3f223f553f753f80,0xbef1be483dc93ec4,0xbf7fbf7bbf62bf35,0xbe95bf0ebf46bf6d,
0xbeb8bd493e893f0e,0xbf7fbf78bf58bf22,0x3f513f183ea10000,0x3f4a3f713f803f75,0x3f393f673f7e3f7b,0xbee6be163e2f3ef1,0xbe60bf04bf42bf6d,0x3f5f3f2c3ecf3dc9,
0xbf6fbf80bf77bf55,0x3d97be79bf09bf46,0x3f133f4e3f733f80,0xbf1dbeacbcc93e95,0xbf31bedbbdfb3e48,0xbf65bf7dbf7cbf62,0x3f7a3f5c3f273ec4,0x3efc3f3e3f6a3f7f,
0xbf78bf7fbf67bf35,0x3d49be95bf18bf55,0x3f7d3f623f2c3ec4,0x3eac3f223f5c3f7b,0xbf04bf46bf71bf80,0x3f3e3ef13e16be48,0x3f4e3f753f803f6d,0xbedbbdc93e793f0e,
0x3e79bdc9bedbbf35,0x3f803f753f4e3f0e,0x3e163ef13f3e3f6d,0xbf71bf46bf04be48,0x3f5c3f223eac8000,0x3f2c3f623f7d3f7b,0xbf18be953d493ec4,0xbf67bf7fbf78bf55,
0x3efc3e16be60bf0e,0x3f6a3f803f733f46,0xbf27beac3cc93ec4,0xbf51bf78bf7ebf62,0x3f4a3f043e2fbe48,0x3f313f673f7f3f75,0xbf65bf2cbeb80000,0xbf09bf4ebf77bf7f,
0x3f5f3f7d3f7a3f55,0xbecfbd493ea13f22,0xbf42bf71bf80bf6d,0x3f133e79bdfbbef1,0x3f1d3f5c3f7c3f7b,0xbf39bedbbd973e95,0xbee6bf3ebf6fbf80,0x3f583f183e89bdc9,
0x3ec43f353f6d3f80,0xbf6dbf35bec40000,0xbec4bf35bf6dbf80,0x3f6d3f353ec40000,0x3ec43f353f6d3f80,0xbf6dbf35bec40000,0xbec4bf35bf6dbf80,0x3f6d3f353ec40000,
0xbf6dbf35bec48000,0xbec4bf35bf6dbf80,0x3f6d3f353ec48000,0x3ec43f353f6d3f80,0xbf6dbf35bec48000,0xbec4bf35bf6dbf80,0x3f6d3f353ec48000,0x3ec43f353f6d3f80,
0xbf7ebf5cbf13be48,0xbcc9bedbbf42bf75,0x3f733f3e3ecf0000,0x3e603f183f5f3f7f,0xbf77bf7dbf58bf0e,0x3eb8bd49bee6bf46,0x3f7f3f713f393ec4,0xbe2f3e793f1d3f62,
0xbdfbbf04bf51bf7b,0x3f803f673f273e95,0x3ea13f2c3f6a3f80,0xbf7abf4ebefcbdc9,0x3e89be16bf09bf55,0x3f6f3f803f653f22,0xbd973eac3f313f6d,0xbf7cbf78bf4abef1,
0x3f043dc9beacbf35,0x3f3e3f753f7d3f55,0xbf4ebef1bd493ec4,0xbedbbf46bf78bf7b,0xbe79bf22bf67bf80,0x3f803f623f183e48,0xbe163e953f2c3f6d,0xbf71bf7fbf5cbf0e,
0x3f5c3f7f3f713f35,0xbf2cbe953e163f0e,0xbf18bf62bf80bf6d,0x3f673f223e79be48,0x3f783f463edb8000,0x3d493ef13f4e3f7b,0xbf7dbf75bf3ebec4,0x3eacbdc9bf04bf55,
0xbcc93edb3f4a3f7b,0xbf73bf7dbf51bef1,0xbf09bf5cbf7fbf6d,0x3f773f3e3eb8bdc9,0x3f6a3f803f5f3f0e,0xbf27be793e603f22,0xbf7cbf4ebee60000,0x3dfbbeacbf39bf75,
0xbf80bf67bf1dbe48,0x3ea1be16bf13bf62,0x3f583f043d97bec4,0x3e893f2c3f6f3f7f,0xbecf3d493efc3f55,0xbf42bf78bf7abf46,0xbe2fbf18bf65bf80,0x3f7e3f713f313e95,
0x3dc93f0e3f623f80,0xbf75bf7bbf46bec4,0x3f223e48be95bf35,0x3ef13f553f7f3f6d,0xbf7fbf55bef10000,0x3e95be48bf22bf6d,0x3f463f7b3f753f35,0xbf62bf0ebdc93ec4,
0xbf7fbf55bef18000,0x3e95be48bf22bf6d,0x3f463f7b3f753f35,0xbf62bf0ebdc93ec4,0xbdc9bf0ebf62bf80,0x3f753f7b3f463ec4,0xbf22be483e953f35,0xbef1bf55bf7fbf6d,
0xbf13bf67bf7fbf55,0x3f7e3f4e3ecfbdc9,0x3f803f5c3efc0000,0xbee63d493f093f62,0x3f7a3f3e3ea1be48,0xbe893e793f313f75,0xbeb83e163f1d3f6d,0xbf27bf71bf7cbf46,
0x3f513edbbd97bf0e,0x3dfb3f183f6a3f7f,0x3cc93f043f5f3f80,0xbf65bf80bf58bef1,0x3e603f2c3f733f7b,0xbf77bf78bf39be95,0xbf6fbf7dbf4abec4,0x3f423eacbe2fbf22,
0x3f2c3f753f783f35,0xbf7dbf46beac3e48,0x3edbbdc9bf18bf6d,0x3f043f623f803f55,0x3d49bef1bf5cbf80,0x3f4e3f7f3f673f0e,0xbf71bf22be163ec4,0x3e79be95bf3ebf7b,
0xbf3ebe953e793f35,0xbe16bf22bf71bf7b,0x3f673f7f3f4e3ec4,0xbf5cbef13d493f0e,0x3f803f623f048000,0xbf18bdc93edb3f55,0xbeacbf46bf7dbf6d,0x3f783f753f2c3e48,
0xbee6bf5cbf80bf55,0x3f7a3f713f1d3dc9,0x3f773f2c3e2fbec4,0xbecf3e163f273f75,0x3d973f183f6f3f7b,0xbf51bf80bf5fbef1,0xbf7ebf67bf090000,0x3f393e79bea1bf46,
0x3f653f04bcc9bf0e,0xbe603eac3f4a3f7f,0x3e893f3e3f7c3f6d,0xbf6abf7dbf42be95,0xbf7fbf4ebeb83e48,0x3f133d49befcbf62,0x3dfbbedbbf58bf80,0x3f313f783f733f22,
0xbe483ec43f553f80,0xbf0ebf6dbf7bbf35,0x3f7b3f6d3f0e0000,0xbf55bec43e483f35,0x3e48bec4bf55bf80,0x3f0e3f6d3f7b3f35,0xbf7bbf6dbf0e0000,0x3f553ec4be48bf35,
0xbf7bbf6dbf0e8000,0x3f553ec4be48bf35,0xbe483ec43f553f80,0xbf0ebf6dbf7bbf35,0x3f7b3f6d3f0e8000,0xbf55bec43e483f35,0x3e48bec4bf55bf80,0x3f0e3f6d3f7b3f35,
0x3ee6be16bf31bf7b,0x3e603f3e3f7e3f62,0x3f773f713f130000,0xbf6abf043d973f22,0xbf42be793eb83f55,0x3e2fbedbbf5fbf7f,0xbf4abf80bf58bec4,0x3f803f4e3ea1be95,
0x3f653f7d3f393e48,0xbf7abf2cbdfb3ef1,0xbe893eac3f513f80,0xbecfbf5cbf7fbf46,0xbf27bf78bf6fbf0e,0x3f7c3f673efcbdc9,0x3f1d3d49bf09bf6d,0x3cc93f183f733f75,
0xbf67bef13e163f35,0x3f04bdc9bf2cbf7b,0x3d493f223f783f6d,0xbf18bf75bf71bf0e,0x3eacbe95bf4ebf80,0x3e793f463f803f55,0xbf3ebf7fbf5cbec4,0x3f7d3f623edbbe48,
0xbedbbf62bf7dbf35,0x3f5c3f7f3f3e3e48,0xbf80bf46be793ec4,0x3f4e3e95beacbf55,0x3f713f753f188000,0xbf78bf22bd493f0e,0x3f2c3dc9bf04bf6d,0xbe163ef13f673f7b,
0x3f513f803f423e48,0xbf7ebf5cbeb83e95,0xbcc93f183f773f6d,0xbee6bf67bf7abf22,0xbf58beac3ea13f55,0x3efcbe16bf39bf7f,0xbf6abf78bf1d0000,0x3f7f3f3e3e2fbef1,
0xbf133d493f273f7b,0x3dfbbf04bf6fbf75,0xbf80bf4ebe893ec4,0x3f653edbbe60bf46,0xbf09bf71bf73bf0e,0x3f5f3f7d3f313dc9,0x3ecfbe79bf4abf80,0x3d973f2c3f7c3f62,
0xbef13e483f463f80,0x3dc9bf0ebf75bf6d,0x3e953f553f7f3f35,0xbf22bf7bbf62bec4,0x3f623f7b3f220000,0xbf7fbf55be953ec4,0x3f753f0ebdc9bf35,0xbf46be483ef13f6d,
0xbf62bf7bbf228000,0x3f7f3f553e95bec4,0xbf75bf0e3dc93f35,0x3f463e48bef1bf6d,0xbef13e483f463f80,0x3dc9bf0ebf75bf6d,0x3e953f553f7f3f35,0xbf22bf7bbf62bec4,
0x3f803f3e3dfbbf0e,0xbf73bf043e2f3f46,0x3f583f7d3f270000,0xbf77bf67becf3e95,0x3eb8beacbf5fbf7b,0xbd973f183f7a3f62,0x3f513e79bee6bf6d,0xbf1d3d493f313f7f,
0x3cc93f2c3f7e3f55,0xbea1bf5cbf7cbf22,0xbf093e163f423f80,0x3e89bedbbf6abf75,0x3f6f3f713efcbe48,0xbf7fbf4ebe603ef1,0x3f133f783f653ec4,0xbf4abf80bf39bdc9,
0xbe16bf46bf80bf35,0x3eac3f623f783f0e,0xbf04bf75bf67bec4,0x3f2c3f7f3f4e3e48,0x3f18bdc9bf3ebf80,0xbedb3e953f5c3f7b,0x3e79bef1bf71bf6d,0xbd493f223f7d3f55,
0x3f7d3f22bd49bf35,0xbf71bef13e793f55,0x3f5c3e95bedbbf6d,0xbf3ebdc93f183f7b,0x3f4e3f7f3f2c8000,0xbf67bf75bf043e48,0x3f783f623eacbec4,0xbf80bf46be163f0e,
0xbf7ebf4ebe2f3f0e,0x3f803f3e3d97bf22,0xbf73bf67beb83ec4,0x3f7a3f5c3e89bef1,0xbf5fbf78bf093e48,0x3f6a3f713ee6be95,0xbf42bf80bf310000,0x3f513f7d3f1dbdc9,
0x3dfbbf18bf7cbf55,0xbcc93f2c3f7f3f46,0x3ea1bedbbf6fbf6d,0xbe603f043f773f62,0x3efcbe79bf58bf7b,0xbecf3eac3f653f75,0x3f27bd49bf39bf80,0xbf133e163f4a3f7f,
0x3f003f003f003f00,0x3f003f003f003f00,0x3f003f003f003f00,0x3f003f003f003f00,0x3f003f003f003f00,0x3f003f003f003f00,0x3f003f003f003f00,0x3f003f003f003f00,
0xbf003f00bf003f00,0xbf003f00bf003f00,0xbf003f00bf003f00,0xbf003f00bf003f00,0xbf003f00bf003f00,0xbf003f00bf003f00,0xbf003f00bf003f00,0xbf003f00bf003f00,
0x3f5f3f5c3f583f55,0x3f6a3f673f653f62,0x3f423f3e3f393f35,0x3f513f4e3f4a3f46,0x3f7e3f7d3f7c3f7b,0x3f803f803f7f3f7f,0x3f733f713f6f3f6d,0x3f7a3f783f773f75,
0x3efc3f043f093f0e,0x3ecf3edb3ee63ef1,0x3f273f2c3f313f35,0x3f133f183f1d3f22,0x3dfb3e163e2f3e48,0x3cc93d493d973dc9,0x3ea13eac3eb83ec4,0x3e603e793e893e95,
0x3f4e3f463f3e3f35,0x3f673f623f5c3f55,0x3f783f753f713f6d,0x3f803f7f3f7d3f7b,0x3e163dc93d490000,0x3eac3e953e793e48,0x3f043ef13edb3ec4,0x3f2c3f223f183f0e,
0x3f183f223f2c3f35,0x3edb3ef13f043f0e,0x3e793e953eac3ec4,0x3d493dc93e163e48,0x3f7d3f7f3f803f80,0x3f713f753f783f7b,0x3f5c3f623f673f6d,0x3f3e3f463f4e3f55,
0x3f6f3f673f5f3f55,0x3f7f3f7d3f7a3f75,0x3f133f043ee63ec4,0x3f4a3f3e3f313f22,0x3cc9bd49bdfbbe48,0x3ea13e793e2f3dc9,0xbf09bf18bf27bf35,0xbe89beacbecfbef1,
0x3eb83edb3efc3f0e,0x3d973e163e603e95,0x3f513f5c3f653f6d,0x3f1d3f2c3f393f46,0x3f803f803f7e3f7b,0x3f733f783f7c3f7f,0x3f583f4e3f423f35,0x3f773f713f6a3f62,
0xbf75bf7bbf7fbf80,0xbf46bf55bf62bf6d,0xbef1bf0ebf22bf35,0xbdc9be48be95bec4,0x3e953e483dc90000,0x3f223f0e3ef13ec4,0x3f623f553f463f35,0x3f7f3f7b3f753f6d,
0x3e953e483dc98000,0x3f223f0e3ef13ec4,0x3f623f553f463f35,0x3f7f3f7b3f753f6d,0x3f753f7b3f7f3f80,0x3f463f553f623f6d,0x3ef13f0e3f223f35,0x3dc93e483e953ec4,
0xbf58bf67bf73bf7b,0xbefcbf18bf31bf46,0xbf6abf5cbf4abf35,0xbf7fbf80bf7cbf75,0x3f513f3e3f273f0e,0x3f7e3f783f6f3f62,0xbcc9be16be89bec4,0x3ee63eac3e603dc9,
0x3f093edb3ea13e48,0x3f5f3f4e3f393f22,0xbecfbf04bf1dbf35,0x3d97bd49be2fbe95,0x3f133f2c3f423f55,0x3dfb3e793eb83ef1,0x3f803f7d3f773f6d,0x3f653f713f7a3f7f,
0xbeacbef1bf18bf35,0x3e793dc9bd49be48,0x3f3e3f223f043ec4,0x3f7d3f753f673f55,0xbedbbe95be160000,0xbf5cbf46bf2cbf0e,0xbf80bf7fbf78bf6d,0xbf4ebf62bf71bf7b,
0x3f713f623f4e3f35,0x3f783f7f3f803f7b,0x3f2c3f463f5c3f6d,0x3e163e953edb3f0e,0xbf67bf75bf7dbf80,0xbf04bf22bf3ebf55,0x3d49bdc9be79bec4,0x3f183ef13eac3e48,
0x3f273f043eb83e48,0x3f7c3f713f5f3f46,0xbf1dbf3ebf58bf6d,0x3cc9be16bea1bef1,0xbf65bf4ebf31bf0e,0xbf7abf80bf7ebf75,0x3e893edb3f133f35,0xbecfbe79bd973dc9,
0x3f423f5c3f6f3f7b,0x3e2f3eac3efc3f22,0x3f4a3f2c3f093ec4,0x3f803f7d3f733f62,0xbee6bf18bf39bf55,0x3e603d49bdfbbe95,0xbf77bf67bf51bf35,0xbf6abf78bf7fbf7f,
0x3f553f6d3f7b3f80,0x3e483ec43f0e3f35,0xbf0ebec4be480000,0xbf7bbf6dbf55bf35,0xbf55bf6dbf7bbf80,0xbe48bec4bf0ebf35,0x3f0e3ec43e480000,0x3f7b3f6d3f553f35,
0xbf0ebec4be488000,0xbf7bbf6dbf55bf35,0xbf55bf6dbf7bbf80,0xbe48bec4bf0ebf35,0x3f0e3ec43e488000,0x3f7b3f6d3f553f35,0x3f553f6d3f7b3f80,0x3e483ec43f0e3f35,
0xbd973e163eb83f0e,0xbf51bf2cbefcbe95,0x3f7e3f713f583f35,0x3f393f5c3f733f7f,0x3ee63e793cc9be48,0x3f7a3f673f4a3f22,0xbf77bf80bf7cbf6d,0xbecfbf18bf42bf62,
0xbf7fbf7dbf6fbf55,0xbf13bf3ebf5fbf75,0x3dfb3eac3f093f35,0xbf31bf04bea1bdc9,0x3f653f783f803f7b,0x3e603edb3f1d3f46,0x3e893d49be2fbec4,0x3f6a3f4e3f273ef1,
0xbf80bf75bf5cbf35,0xbf18bf46bf67bf7b,0x3eac3dc9be16bec4,0x3f783f623f3e3f0e,0x3f2c3ef13e790000,0x3f7d3f7f3f713f55,0x3edb3f223f4e3f6d,0xbf04be95bd493e48,
0xbd49be95bf04bf35,0x3f4e3f223edb3e48,0x3f713f7f3f7d3f6d,0x3e793ef13f2c3f55,0x3f3e3f623f783f80,0xbe163dc93eac3f0e,0xbf67bf46bf18bec4,0xbf5cbf75bf80bf7b,
0x3e60bd49bea1bf0e,0x3f773f5c3f313ef1,0xbf6fbf4ebf1dbec4,0xbf42bf67bf7cbf7f,0x3f513f713f7f3f7b,0xbdfb3e163ecf3f22,0x3cc9be79befcbf35,0x3f653f3e3f093e95,
0x3f7a3f803f733f55,0x3e893f043f393f62,0xbeb8bf18bf4abf6d,0x3f273edb3e2fbdc9,0xbf13beacbd973e48,0xbf7ebf7dbf6abf46,0x3f803f783f5f3f35,0x3ee63f2c3f583f75,
0xbf22bf55bf75bf80,0x3ef13e48bdc9bec4,0x3f7f3f7b3f623f35,0x3e953f0e3f463f6d,0xbf46bf0ebe950000,0xbf62bf7bbf7fbf6d,0x3dc9be48bef1bf35,0x3f753f553f223ec4,
0x3f463f0e3e958000,0x3f623f7b3f7f3f6d,0xbdc93e483ef13f35,0xbf75bf55bf22bec4,0xbf22bf55bf75bf80,0x3ef13e48bdc9bec4,0x3f7f3f7b3f623f35,0x3e953f0e3f463f6d,
0x3f6a3f3e3efc3e48,0x3f273f5c3f7a3f7f,0xbf7cbf7dbf65bf35,0xbdfbbedbbf31bf62,0xbcc9beacbf1dbf55,0x3f733f4e3f133e95,0xbf09be793d973ec4,0xbf77bf80bf6fbf46,
0x3ecf3f2c3f5f3f7b,0xbf42bf04be603dc9,0x3e2fbe16bee6bf35,0x3f7e3f673f393ef1,0x3f803f713f4a3f0e,0x3ea13f183f513f75,0xbf58bf78bf7fbf6d,0x3e89bd49beb8bf22,
0xbe793dc93edb3f35,0xbf80bf75bf4ebf0e,0xbe16bef1bf3ebf6d,0x3f713f463f043e48,0xbf5cbf22beac0000,0xbf2cbf62bf7dbf7b,0x3f183e95bd49bec4,0x3f673f7f3f783f55,
0xbf78bf7fbf67bf35,0x3d49be95bf18bf55,0x3f7d3f623f2c3ec4,0x3eac3f223f5c3f7b,0xbf04bf46bf71bf80,0x3f3e3ef13e16be48,0x3f4e3f753f803f6d,0xbedbbdc93e793f0e,
0xbe89bf18bf58bf7b,0x3f6f3f3e3ee63dc9,0x3d973edb3f393f6d,0xbf7cbf5cbf1dbe95,0x3dfbbe79bf13bf55,0x3f803f713f423ef1,0xbea13d493ecf3f35,0xbf7abf7dbf5fbf22,
0x3f773f4e3f093e48,0x3eb83f2c3f653f7f,0xbf7fbf67bf31bec4,0xbe2fbf04bf4abf75,0x3f7e3f783f513f0e,0xbcc93eac3f273f62,0xbf73bf80bf6abf35,0x3e60be16befcbf46,
0x3ec43f353f6d3f80,0xbf6dbf35bec40000,0xbec4bf35bf6dbf80,0x3f6d3f353ec40000,0x3ec43f353f6d3f80,0xbf6dbf35bec40000,0xbec4bf35bf6dbf80,0x3f6d3f353ec40000,
0xbf6dbf35bec48000,0xbec4bf35bf6dbf80,0x3f6d3f353ec48000,0x3ec43f353f6d3f80,0xbf6dbf35bec48000,0xbec4bf35bf6dbf80,0x3f6d3f353ec48000,0x3ec43f353f6d3f80,
0xbf4abf78bf7cbf55,0x3f313eacbd97bef1,0x3f653f803f6f3f35,0xbf09be163e893f22,0xbefcbf4ebf7abf7b,0x3f6a3f2c3ea1bdc9,0x3f273f673f803f6d,0xbf51bf04bdfb3e95,
0x3f1d3e79be2fbf0e,0x3f393f713f7f3f62,0xbee6bd493eb83f35,0xbf58bf7dbf77bf46,0x3f5f3f183e60be48,0x3ecf3f3e3f733f7f,0xbf42bedbbcc93ec4,0xbf13bf5cbf7ebf75,
0x3f5c3f7f3f713f35,0xbf2cbe953e163f0e,0xbf18bf62bf80bf6d,0x3f673f223e79be48,0x3f783f463edb0000,0x3d493ef13f4e3f7b,0xbf7dbf75bf3ebec4,0x3eacbdc9bf04bf55,
0xbf04bdc93eac3f35,0xbf3ebf75bf7dbf55,0x3f4e3ef13d49bec4,0x3edb3f463f783f7b,0x3e793f223f673f80,0xbf80bf62bf18be48,0x3e16be95bf2cbf6d,0x3f713f7f3f5c3f0e,
0xbf31bf71bf7ebf55,0x3f653f183e2fbe95,0x3f7a3f783f423ec4,0xbefcbd493ecf3f46,0xbf6fbf2cbe893e48,0xbd97bf04bf58bf7f,0x3f133e16bea1bf35,0x3f1d3f673f803f62,
0x3f393eacbdfbbf0e,0x3ee63f4e3f7c3f75,0xbe603e793f273f6d,0xbf5fbf80bf6abf22,0xbeb8bf3ebf77bf7b,0x3f7f3f5c3f093dc9,0x3f513f7d3f733f35,0xbf4abedb3cc93ef1,
0xbdc9bf0ebf62bf80,0x3f753f7b3f463ec4,0xbf22be483e953f35,0xbef1bf55bf7fbf6d,0x3f7f3f553ef10000,0xbe953e483f223f6d,0xbf46bf7bbf75bf35,0x3f623f0e3dc9bec4,
0x3f7f3f553ef18000,0xbe953e483f223f6d,0xbf46bf7bbf75bf35,0x3f623f0e3dc9bec4,0x3dc93f0e3f623f80,0xbf75bf7bbf46bec4,0x3f223e48be95bf35,0x3ef13f553f7f3f6d,
0xbe2f3eac3f423f7b,0xbf4abf7dbf6fbf22,0xbf39bf78bf77bf35,0x3f733f2c3e60be95,0xbf58bf80bf65bf0e,0x3f5f3f043cc9bef1,0x3f6a3f183dfbbec4,0xbd973edb3f513f7f,
0xbf7cbf71bf27be48,0x3f1d3e16beb8bf46,0x3f313e79be89bf35,0x3ea13f3e3f7a3f75,0x3f093d49bee6bf55,0x3efc3f5c3f803f62,0x3ecf3f4e3f7e3f6d,0xbf7fbf67bf13bdc9,
0x3f3e3e95be79bf35,0x3e163f223f713f7b,0xbf67bf7fbf4ebec4,0x3f5c3ef1bd49bf0e,0xbf80bf62bf040000,0x3f183dc9bedbbf55,0x3eac3f463f7d3f6d,0xbf78bf75bf2cbe48,
0x3f2c3f753f783f35,0xbf7dbf46beac3e48,0x3edbbdc9bf18bf6d,0x3f043f623f803f55,0x3d49bef1bf5cbf80,0x3f4e3f7f3f673f0e,0xbf71bf22be163ec4,0x3e79be95bf3ebf7b,
0xbf73bf78bf31be48,0x3f583edbbdfbbf22,0x3efcbd49bf13bf6d,0x3eb83f4e3f7f3f62,0x3f423f7d3f6a3f0e,0xbf7cbf3ebe893e95,0xbf4abeac3e603f35,0x3cc9bf04bf65bf7f,
0x3ea1be79bf39bf7b,0x3f093f673f7e3f46,0x3f5f3f803f513ec4,0xbf6fbf18bd973ef1,0xbf27be163ecf3f55,0xbe2fbf2cbf77bf75,0xbf1dbf71bf7abf35,0x3f803f5c3ee6bdc9,
0xbe483ec43f553f80,0xbf0ebf6dbf7bbf35,0x3f7b3f6d3f0e0000,0xbf55bec43e483f35,0x3e48bec4bf55bf80,0x3f0e3f6d3f7b3f35,0xbf7bbf6dbf0e0000,0x3f553ec4be48bf35,
0xbf7bbf6dbf0e8000,0x3f553ec4be48bf35,0xbe483ec43f553f80,0xbf0ebf6dbf7bbf35,0x3f7b3f6d3f0e8000,0xbf55bec43e483f35,0x3e48bec4bf55bf80,0x3f0e3f6d3f7b3f35,
0x3f733f183cc9bf0e,0xbf093d493f1d3f75,0x3efc3f673f7c3f35,0xbf6fbf78bf27bdc9,0xbf7fbf5cbecf3e48,0x3f513eacbe89bf46,0xbdfbbf2cbf7abf6d,0x3f393f7d3f653ef1,
0x3ea13f4e3f803f55,0xbf58bf80bf4abe95,0xbf5fbedb3e2f3f35,0x3eb8be79bf42bf7f,0x3d97bf04bf6abf7b,0x3f133f713f773f22,0x3f7e3f3e3e60bec4,0xbf31be163ee63f62,
0xbedbbf62bf7dbf35,0x3f5c3f7f3f3e3e48,0xbf80bf46be793ec4,0x3f4e3e95beacbf55,0x3f713f753f180000,0xbf78bf22bd493f0e,0x3f2c3dc9bf04bf6d,0xbe163ef13f673f7b,
0x3f673ef1be16bf35,0xbf043dc93f2c3f7b,0xbd49bf22bf78bf6d,0x3f183f753f713f0e,0xbeac3e953f4e3f80,0xbe79bf46bf80bf55,0x3f3e3f7f3f5c3ec4,0xbf7dbf62bedb3e48,
0xbf7cbf2cbd973f0e,0x3f4a3e79becfbf62,0xbf31bf7dbf5fbec4,0x3f733f713f09bdc9,0x3e60bedbbf65bf7b,0x3e893f4e3f803f46,0x3f6f3f04bdfbbf35,0xbf27bd493f133f75,
0xbe2fbf3ebf7fbf55,0x3f1d3f783f6a3ef1,0x3f393e16befcbf6d,0xbea13eac3f583f7f,0x3f7a3f673ee6be48,0xbf77bf183cc93f22,0x3eb83f5c3f7e3f35,0xbf42bf80bf51be95,
0x3ef1be48bf46bf80,0xbdc93f0e3f753f6d,0xbe95bf55bf7fbf35,0x3f223f7b3f623ec4,0xbf62bf7bbf220000,0x3f7f3f553e95bec4,0xbf75bf0e3dc93f35,0x3f463e48bef1bf6d,
0x3f623f7b3f228000,0xbf7fbf55be953ec4,0x3f753f0ebdc9bf35,0xbf46be483ef13f6d,0x3ef1be48bf46bf80,0xbdc93f0e3f753f6d,0xbe95bf55bf7fbf35,0x3f223f7b3f623ec4,
0xbf39bf80bf4abe48,0x3f653f783f13bdc9,0xbe60bf4ebf7fbf35,0x3efc3f713f6f3ef1,0xbf6abedb3e893f55,0x3f423e16bf09bf75,0xbf7cbf5cbea13ec4,0x3f7e3f2c3cc9bf22,
0x3f313d49bf1dbf7b,0xbee63e793f513f7f,0x3f7a3f18bd97bf35,0xbf5fbeac3eb83f62,0xbecfbf67bf77bf0e,0x3f273f7d3f583e95,0x3e2fbf04bf73bf6d,0x3dfb3f3e3f803f46,
0xbf7dbf223d493f35,0x3f713ef1be79bf55,0xbf5cbe953edb3f6d,0x3f3e3dc9bf18bf7b,0xbf4ebf7fbf2c0000,0x3f673f753f04be48,0xbf78bf62beac3ec4,0x3f803f463e16bf0e,
0xbe16bf46bf80bf35,0x3eac3f623f783f0e,0xbf04bf75bf67bec4,0x3f2c3f7f3f4e3e48,0x3f18bdc9bf3ebf80,0xbedb3e953f5c3f7b,0x3e79bef1bf71bf6d,0xbd493f223f7d3f55,
0xbf4abe163f133f7b,0x3f393d49bf27bf7f,0xbf65beac3ecf3f6d,0x3f583e79befcbf75,0xbf77bf043e603f55,0x3f6f3edbbea1bf62,0xbf7fbf2c3cc93f35,0x3f7c3f18bdfbbf46,
0xbf1dbf7dbf51be48,0x3f313f803f423dc9,0xbee6bf71bf6abec4,0x3f093f783f5f3e95,0xbe89bf5cbf7abf0e,0x3eb83f673f733ef1,0xbd97bf3ebf80bf35,0x3e2f3f4e3f7e3f22,
0xbf8000003f80,0xbf8000003f80,0xbf8000003f80,0xbf8000003f80,0xbf8000003f80,0xbf8000003f80,0xbf8000003f80,0xbf8000003f80,
0x3f808000bf808000,0x3f808000bf808000,0x3f808000bf808000,0x3f808000bf808000,0x3f808000bf808000,0x3f808000bf808000,0x3f808000bf808000,0x3f808000bf808000,
0xbf77be793f7a3e48,0xbf6fbeac3f733e95,0xbf7fbd493f800000,0xbf7cbe163f7e3dc9,0xbf4abf183f513f0e,0xbf39bf2c3f423f22,0xbf65bedb3f6a3ec4,0xbf58bf043f5f3ef1,
0x3e89bf78be603f7b,0x3eb8bf71bea13f75,0x3d97bf80bcc93f80,0x3e2fbf7dbdfb3f7f,0x3f1dbf4ebf133f55,0x3f31bf3ebf273f46,0x3ee6bf67becf3f6d,0x3f09bf5cbefc3f62,
0xbf4e3f223f3ebf35,0xbf673ef13f5cbf0e,0xbf783e953f71bec4,0xbf803dc93f7dbe48,0xbe163f7f3d49bf80,0xbeac3f753e79bf7b,0xbf043f623edbbf6d,0xbf2c3f463f18bf55,
0xbf18bf463f2c3f35,0xbedbbf623f043f55,0xbe79bf753eac3f6d,0xbd49bf7f3e163f7b,0xbf7dbdc93f808000,0xbf71be953f783e48,0xbf5cbef13f673ec4,0xbf3ebf223f4e3f0e,
0xbecf3f713e89bf7b,0xbf273f4e3f09bf62,0x3e2f3f78bea1bf6d,0xbdfb3f80bcc9bf7f,0x3f313f2cbf4abf0e,0x3ee63f5cbf13bf46,0x3f7a3e16bf7f0000,0x3f5f3edbbf6fbe95,
0xbf6abeac3f773e48,0xbf42bf183f583ef1,0xbf7c3e793f73bec4,0xbf7ebd493f80bdc9,0xbf393f3e3f1dbf55,0xbf653f043f51bf22,0xbe603f7d3d97bf80,0xbefc3f673eb8bf75,
0x3e95bf7bbdc93f80,0x3f22bf55bef13f6d,0x3f62bf0ebf463f35,0x3f7fbe48bf753ec4,0x3f753e48bf7f0000,0x3f463f0ebf62bec4,0x3ef13f55bf22bf35,0x3dc93f7bbe95bf6d,
0x3f753e48bf7f8000,0x3f463f0ebf62bec4,0x3ef13f55bf22bf35,0x3dc93f7bbe95bf6d,0xbe953f7b3dc9bf80,0xbf223f553ef1bf6d,0xbf623f0e3f46bf35,0xbf7f3e483f75bec4,
0xbe60bf713ee63f55,0x3e89bf7dbcc93f7f,0xbf6fbe793f7e0000,0xbf27bf2c3f513ef1,0x3f7c3d49bf7f3e48,0x3f4a3f04bf6abe95,0x3f31bf4ebefc3f6d,0x3f73bedbbf583f22,
0x3f7abeacbf653f0e,0x3f773e16bf803dc9,0x3eb8bf78bdfb3f80,0x3f42bf3ebf133f62,0xbe2f3f80bd97bf7b,0xbf1d3f5c3ecfbf75,0x3f393f18bf5fbec4,0x3ea13f67bf09bf46,
0xbeacbf623f183f35,0x3e79bf7f3d493f7b,0x3f3ebf46bf043f6d,0x3f7dbe95bf673f0e,0xbedb3f753e16bf80,0xbf5c3f223f2cbf55,0xbf803dc93f78bec4,0xbf4ebef13f713e48,
0x3f71bef1bf4e3f35,0x3f783dc9bf803e48,0x3f2c3f22bf5cbec4,0x3e163f75bedbbf55,0xbf67be953f7d8000,0xbf04bf463f3e3f0e,0x3d49bf7f3e793f6d,0x3f18bf62beac3f7b,
0xbd97bf783ecf3f55,0x3f13bf67be893f7f,0xbf7e3d493f7abec4,0xbf31bf183f653e95,0xbea13f7dbcc9bf7b,0xbf583f2c3f1dbf62,0x3f5f3eacbf7c0000,0x3eb83f5cbf27bf22,
0x3f7fbe79bf6a3f0e,0x3f513edbbf77bdc9,0x3dfbbf803e603f6d,0x3f39bf4ebee63f75,0xbf73be163f80be48,0xbf09bf3e3f4a3ef1,0xbefc3f713e2fbf80,0xbf6f3f043f42bf46,
0x3f0ebf6dbe483f80,0x3f7bbec4bf553f35,0x3f553ec4bf7b0000,0x3e483f6dbf0ebf35,0xbf0e3f6d3e48bf80,0xbf7b3ec43f55bf35,0xbf55bec43f7b0000,0xbe48bf6d3f0e3f35,
0x3f553ec4bf7b8000,0x3e483f6dbf0ebf35,0xbf0e3f6d3e48bf80,0xbf7b3ec43f55bf35,0xbf55bec43f7b8000,0xbe48bf6d3f0e3f35,0x3f0ebf6dbe483f80,0x3f7bbec4bf553f35,
0x3f42bf4ebecf3f7b,0x3f7cbd49bf773ef1,0xbf4abedb3f7a0000,0xbcc9bf783ee63f46,0xbf733f043f39bf55,0xbf58beac3f7ebdc9,0x3efc3f3ebf51bec4,0xbeb83f7dbd97bf75,
0x3f273f18bf6abe48,0xbe2f3f80be89bf62,0x3f1dbf67be603f80,0x3f80be79bf653f22,0xbea1bf5c3f313f0e,0x3f09bf71bdfb3f7f,0xbf5f3f2c3f13bf6d,0xbf6fbe163f7fbe95,
0x3f80be95bf5c3f35,0x3f183f22bf67be48,0xbeac3f7fbe16bf6d,0xbf783ef13f3ebf55,0xbf2c3f623e79bf80,0xbf7d3dc93f71bf0e,0xbedbbf463f4e3ec4,0x3f04bf75bd493f7b,
0x3d493f75bf04bf35,0xbf4e3f463edbbf7b,0xbf71bdc93f7dbec4,0xbe79bf623f2c3f0e,0xbf3ebef13f788000,0x3e16bf7f3eac3f55,0x3f67bf22bf183f6d,0x3f5c3e95bf803e48,
0x3f093f2cbf65be48,0xbefc3f78bcc9bf75,0x3ecfbf7d3dfb3f6d,0x3f7fbeacbf513f46,0xbf7c3edb3f42bf55,0xbf1dbf183f6f3dc9,0x3f313f04bf770000,0xbea13f80be60bf62,
0xbf583f3e3ee6bf7b,0xbf5fbe793f80be95,0x3f6a3e16bf7e3ec4,0x3d973f71bf13bf22,0xbe2fbf673f273f0e,0x3f4abf4ebeb83f7f,0xbf393f5c3e89bf80,0xbf73bd493f7abef1,
0x3f46bf55be953f80,0x3f623e48bf7f3ec4,0xbdc93f7bbef1bf35,0xbf753f0e3f22bf6d,0xbf22bf0e3f750000,0x3ef1bf7b3dc93f6d,0x3f7fbe48bf623f35,0x3e953f55bf46bec4,
0x3f223f0ebf758000,0xbef13f7bbdc9bf6d,0xbf7f3e483f62bf35,0xbe95bf553f463ec4,0x3f46bf55be953f80,0x3f623e48bf7f3ec4,0xbdc93f7bbef1bf35,0xbf753f0e3f22bf6d,
0x3f6f3d49bf773f0e,0xbd973f78bf09bf22,0xbf13bf183f730000,0x3f1dbf71bcc93f75,0x3f31bf67bdfb3f7b,0x3f653e16bf7c3ef1,0xbf7a3f043f27bf6d,0xbefcbf2c3f6a3dc9,
0xbeb83f80be89bf55,0xbf7f3e793f58bf46,0x3f51bf4ebea13f80,0x3f4a3eacbf803e95,0x3f393edbbf7e3e48,0xbee63f7dbe2fbf62,0xbe60bf5c3f423ec4,0x3f5fbf3ebecf3f7f,
0xbe793f7fbedbbf35,0xbf803e953f4ebf55,0xbe16bf623f3e3ec4,0x3f71bf22bf043f7b,0xbf5c3f463eacbf80,0xbf2cbef13f7dbe48,0x3f18bf753d493f6d,0x3f673dc9bf783f0e,
0xbf783dc93f67bf35,0x3d49bf753f183f0e,0x3f7dbef1bf2c3f6d,0x3eac3f46bf5cbe48,0xbf04bf223f718000,0x3f3ebf62be163f7b,0x3f4e3e95bf803ec4,0xbedb3f7fbe79bf55,
0xbf5fbe163f7abf0e,0x3ecfbf803ea13f46,0x3f423eacbf803ec4,0xbf133f78bdfbbf62,0xbf1dbf043f7cbe48,0x3f39bf67bd973f75,0x3ee63f2cbf6f0000,0xbf583f4e3e89bf7f,
0x3efcbf7d3e603f55,0x3f6a3d49bf733f22,0xbf273f71bcc9bf6d,0xbf51be793f7ebef1,0x3f4abf5cbe2f3f7b,0x3f313edbbf7f3e95,0xbf653f3e3eb8bf80,0xbf09bf183f77bdc9,
0x3f6dbf35bec43f80,0x3ec43f35bf6d0000,0xbf6d3f353ec4bf80,0xbec4bf353f6d0000,0x3f6dbf35bec43f80,0x3ec43f35bf6d0000,0xbf6d3f353ec4bf80,0xbec4bf353f6d0000,
0x3ec43f35bf6d8000,0xbf6d3f353ec4bf80,0xbec4bf353f6d8000,0x3f6dbf35bec43f80,0x3ec43f35bf6d8000,0xbf6d3f353ec4bf80,0xbec4bf353f6d8000,0x3f6dbf35bec43f80,
0x3dfb3f5cbf51be48,0xbf803edb3f27bf75,0xbea1bf3e3f6a0000,0x3f7abf18befc3f7f,0xbe893f7dbf09bf0e,0xbf6f3d493f65bf46,0x3d97bf713f313ec4,0x3f7cbe79bf4a3f62,
0xbf7e3f043f13bf7b,0xbcc9bf673f423e95,0x3f73bf2cbecf3f80,0x3e603f4ebf5fbdc9,0xbf773e163f58bf55,0x3eb8bf803ee63f22,0x3f7fbeacbf393f6d,0xbe2f3f78bf1dbef1,
0xbf5cbdc93f71bf35,0x3f2cbf753e163f55,0x3f183ef1bf803ec4,0xbf673f463e79bf7b,0xbf783f223edbbf80,0xbd49bf623f4e3e48,0x3f7dbe95bf3e3f6d,0xbeac3f7fbf04bf0e,
0x3f04bf7f3eac3f35,0x3f3e3e95bf7d3f0e,0xbf4e3f623d49bf6d,0xbedbbf223f78be48,0xbe79bf463f678000,0x3f80bef1bf183f7b,0xbe163f75bf2cbec4,0xbf713dc93f5cbf55,
0x3f80bedbbf1d3f7b,0xbea13f7dbf13bef1,0xbf583f5c3d97bf6d,0xbe89bf3e3f6fbdc9,0x3ecfbf803efc3f0e,0x3f423e79bf7a3f22,0x3e2f3f4ebf650000,0xbf7e3eac3f31bf75,
0xbcc93f67bf4abe48,0xbf733e163f51bf62,0xbf09bf043f7fbec4,0x3f77bf2cbeb83f7f,0x3f6abd49bf5f3f55,0xbf273f78be60bf46,0xbf7c3f183ee6bf80,0x3dfbbf713f393e95,
0x3f7fbf0ebef13f80,0xbe953f7bbf22bec4,0xbf46be483f75bf35,0x3f62bf55bdc93f6d,0x3dc93f55bf620000,0xbf753e483f46bf6d,0x3f22bf7b3e953f35,0x3ef13f0ebf7f3ec4,
0x3dc93f55bf628000,0xbf753e483f46bf6d,0x3f22bf7b3e953f35,0x3ef13f0ebf7f3ec4,0xbf7f3f0e3ef1bf80,0x3e95bf7b3f223ec4,0x3f463e48bf753f35,0xbf623f553dc9bf6d,
0xbf513f67bd97bf55,0xbdfbbf4e3f6abdc9,0xbcc9bf5c3f5f0000,0x3f65bd49bf583f62,0xbe60bf3e3f73be48,0x3f77be79bf393f75,0x3f6fbe16bf4a3f6d,0xbf423f71be2fbf46,
0xbf13bedb3f7fbf0e,0x3f7ebf18becf3f7f,0x3f80bf04befc3f80,0xbee63f80bf09bef1,0x3f7abf2cbea13f7b,0xbe893f78bf31be95,0xbeb83f7dbf1dbec4,0xbf27beac3f7cbf22,
0x3f3ebf753e793f35,0x3e163f46bf713e48,0xbf673dc93f4ebf6d,0x3f5cbf623d493f55,0xbf803ef13f04bf80,0x3f18bf7f3edb3f0e,0x3eac3f22bf7d3ec4,0xbf783e953f2cbf7b,
0x3f2c3e95bf783f35,0xbf7d3f223eacbf7b,0x3edbbf7f3f183ec4,0x3f043ef1bf803f0e,0x3d49bf623f5c8000,0x3f4e3dc9bf673f55,0xbf713f463e16bf6d,0x3e79bf753f3e3e48,
0xbf653f5cbcc9bf55,0x3e60bf713f4a3dc9,0xbe89bf2c3f7cbec4,0x3f6abe16bf423f75,0x3f7fbf18beb83f7b,0xbf133f80befcbef1,0xbdfb3f67bf580000,0xbf31be793f73bf46,
0xbee6bf043f80bf0e,0x3f7abeacbf1d3f7f,0x3f77bf3ebe2f3f6d,0xbecf3f7dbf27be95,0x3d973f4ebf6f3e48,0xbf51bd493f5fbf62,0xbf7e3edb3f09bf80,0x3f39bf783ea13f22,
0x3f7bbec4bf0e3f80,0xbf553f6dbe48bf35,0x3e48bf6d3f550000,0x3f0e3ec4bf7b3f35,0xbf7b3ec43f0ebf80,0x3f55bf6d3e483f35,0xbe483f6dbf550000,0xbf0ebec43f7bbf35,
0xbe483f6dbf558000,0xbf0ebec43f7bbf35,0x3f7bbec4bf0e3f80,0xbf553f6dbe48bf35,0x3e48bf6d3f558000,0x3f0e3ec4bf7b3f35,0xbf7b3ec43f0ebf80,0x3f55bf6d3e483f35,
0xbf653e163f39bf7b,0x3f7abf3ebdfb3f62,0x3e89bf713f510000,0x3ecf3f04bf7f3f22,0x3f273e79bf6f3f55,0xbf7c3edb3efcbf7f,0xbf1d3f80bf09bec4,0xbcc9bf4e3f73be95,
0x3ee6bf7d3f313e48,0x3e603f2cbf7e3ef1,0x3f77beacbf133f80,0xbf6a3f5cbd97bf46,0xbf423f78beb8bf0e,0x3e2fbf673f5fbdc9,0xbf4abd493f58bf6d,0x3f80bf18bea13f75,
0x3edb3ef1bf7d3f35,0xbf5c3dc93f3ebf7b,0x3f80bf22be793f6d,0xbf4e3f75beacbf0e,0xbf713e953f18bf80,0x3f78bf46bd493f55,0xbf2c3f7fbf04bec4,0x3e16bf623f67be48,
0xbf673f62be16bf35,0x3f04bf7f3f2c3e48,0x3d493f46bf783ec4,0xbf18be953f71bf55,0x3eacbf753f4e8000,0x3e793f22bf803f0e,0xbf3ebdc93f5cbf6d,0x3f7dbef1bedb3f7b,
0x3f13bf803f273e48,0xbdfb3f5cbf6f3e95,0x3f80bf18be893f6d,0xbf653f67be60bf22,0x3f093eacbf733f55,0xbf5f3e163f31bf7f,0xbecf3f78bf4a0000,0xbd97bf3e3f7cbef1,
0x3f51bd49bf423f7b,0xbf7e3f043eb8bf75,0xbcc93f4ebf773ec4,0xbee6bedb3f7abf46,0xbf583f71bea1bf0e,0x3efcbf7d3f393dc9,0xbf6a3e793f1dbf80,0x3f7fbf2cbe2f3f62,
0x3f62be48bf223f80,0xbf7f3f0e3e95bf6d,0x3f75bf553dc93f35,0xbf463f7bbef1bec4,0x3ef1bf7b3f460000,0xbdc93f55bf753ec4,0xbe95bf0e3f7fbf35,0x3f223e48bf623f6d,
0xbef13f7bbf468000,0x3dc9bf553f75bec4,0x3e953f0ebf7f3f35,0xbf22be483f62bf6d,0x3f62be48bf223f80,0xbf7f3f0e3e95bf6d,0x3f75bf553dc93f35,0xbf463f7bbef1bec4,
0xbcc9bf3e3f7ebf0e,0x3ea13f04bf7c3f46,0x3f09bf7d3f420000,0xbe893f67bf6a3e95,0xbf6f3eac3efcbf7b,0x3f7fbf18be603f62,0xbf13be793f65bf6d,0x3f4abd49bf393f7f,
0x3f80bf2cbdfb3f55,0xbf733f5cbe2fbf22,0x3f58be16bf273f80,0xbf773edb3ecfbf75,0x3eb8bf713f5fbe48,0xbd973f4ebf7a3ef1,0x3f51bf783ee63ec4,0xbf1d3f80bf31bdc9,
0xbf7d3f46bd49bf35,0x3f71bf623e793f0e,0xbf5c3f75bedbbec4,0x3f3ebf7f3f183e48,0xbf4e3dc93f2cbf80,0x3f67be95bf043f7b,0xbf783ef13eacbf6d,0x3f80bf22be163f55,
0xbe16bf223f80bf35,0x3eac3ef1bf783f55,0xbf04be953f67bf6d,0x3f2c3dc9bf4e3f7b,0x3f18bf7f3f3e8000,0xbedb3f75bf5c3e48,0x3e79bf623f71bec4,0xbd493f46bf7d3f0e,
0xbdfb3f4ebf7c3f0e,0x3cc9bf3e3f7fbf22,0xbea13f67bf6f3ec4,0x3e60bf5c3f77bef1,0xbefc3f78bf583e48,0x3ecfbf713f65be95,0xbf273f80bf390000,0x3f13bf7d3f4abdc9,
0xbf7e3f183e2fbf55,0x3f80bf2cbd973f46,0xbf733edb3eb8bf6d,0x3f7abf04be893f62,0xbf5f3e793f09bf7b,0x3f6abeacbee63f75,0xbf423d493f31bf80,0x3f51be16bf1d3f7f,
0xbf8000003f80,0xbf8000003f80,0xbf8000003f80,0xbf8000003f80,0xbf8000003f80,0xbf8000003f80,0xbf8000003f80,0xbf8000003f80,
0x3f808000bf808000,0x3f808000bf808000,0x3f808000bf808000,0x3f808000bf808000,0x3f808000bf808000,0x3f808000bf808000,0x3f808000bf808000,0x3f808000bf808000,
0xbefcbf5c3f093f55,0xbecfbf673ee63f62,0xbf27bf3e3f313f35,0xbf13bf4e3f1d3f46,0xbdfbbf7d3e2f3f7b,0xbcc9bf803d973f7f,0xbea1bf713eb83f6d,0xbe60bf783e893f75,
0x3f5fbf04bf583f0e,0x3f6abedbbf653ef1,0x3f42bf2cbf393f35,0x3f51bf18bf4a3f22,0x3f7ebe16bf7c3e48,0x3f80bd49bf7f3dc9,0x3f73beacbf6f3ec4,0x3f7abe79bf773e95,
0xbf18bf463f2c3f35,0xbedbbf623f043f55,0xbe79bf753eac3f6d,0xbd49bf7f3e163f7b,0xbf7dbdc93f800000,0xbf71be953f783e48,0xbf5cbef13f673ec4,0xbf3ebf223f4e3f0e,
0x3f4ebf22bf3e3f35,0x3f67bef1bf5c3f0e,0x3f78be95bf713ec4,0x3f80bdc9bf7d3e48,0x3e16bf7fbd493f80,0x3eacbf75be793f7b,0x3f04bf62bedb3f6d,0x3f2cbf46bf183f55,
0xbeb8bf673efc3f55,0xbd97bf7d3e603f75,0xbf51bf043f653ec4,0xbf1dbf3e3f393f22,0xbf803d493f7ebe48,0xbf73be793f7c3dc9,0xbf583f183f42bf35,0xbf773eac3f6abef1,
0x3f6fbedbbf5f3f0e,0x3f7fbe16bf7a3e95,0x3f13bf5cbee63f6d,0x3f4abf2cbf313f46,0x3cc9bf803dfb3f7b,0x3ea1bf78be2f3f7f,0xbf09bf4e3f273f35,0xbe89bf713ecf3f62,
0xbe953f7b3dc9bf80,0xbf223f553ef1bf6d,0xbf623f0e3f46bf35,0xbf7f3e483f75bec4,0xbf75be483f7f0000,0xbf46bf0e3f623ec4,0xbef1bf553f223f35,0xbdc9bf7b3e953f6d,
0xbf75be483f7f8000,0xbf46bf0e3f623ec4,0xbef1bf553f223f35,0xbdc9bf7b3e953f6d,0x3e95bf7bbdc93f80,0x3f22bf55bef13f6d,0x3f62bf0ebf463f35,0x3f7fbe48bf753ec4,
0xbf093f673ea1bf7b,0xbf5f3f183f39bf46,0x3ecf3f5cbf1dbf35,0xbd973f80be2fbf75,0xbf13bf3e3f423f0e,0xbdfbbf783eb83f62,0xbf803e163f77bec4,0xbf65beac3f7a3dc9,
0xbf58bedb3f733e48,0xbefcbf4e3f313f22,0xbf6a3f043f4abf35,0xbf7f3d493f7cbe95,0x3f51bf2cbf273f55,0x3f7ebe79bf6f3ef1,0xbcc9bf7d3e893f6d,0x3ee6bf71be603f7f,
0xbf713ef13f4ebf35,0xbf78bdc93f80be48,0xbf2cbf223f5c3ec4,0xbe16bf753edb3f55,0x3f673e95bf7d0000,0x3f043f46bf3ebf0e,0xbd493f7fbe79bf6d,0xbf183f623eacbf7b,
0xbeacbf623f183f35,0x3e79bf7f3d493f7b,0x3f3ebf46bf043f6d,0x3f7dbe95bf673f0e,0xbedb3f753e16bf80,0xbf5c3f223f2cbf55,0xbf803dc93f78bec4,0xbf4ebef13f713e48,
0xbf42bf043f6f3e48,0xbe2fbf713efc3f46,0xbf4a3f3e3f09bf6d,0xbf803e163f73bef1,0x3ee63f4ebf39bf0e,0xbe603f80bdfbbf75,0x3f77bedbbf513f35,0x3f6a3e79bf7f3dc9,
0x3f27bf5cbeb83f7b,0x3f7cbeacbf5f3f22,0xbf1dbf2c3f583ec4,0x3cc9bf7d3ea13f62,0xbf653f183f31bf55,0xbf7abd493f7ebe95,0x3e893f67bf13bf35,0xbecf3f783d97bf7f,
0x3f0ebf6dbe483f80,0x3f7bbec4bf553f35,0x3f553ec4bf7b0000,0x3e483f6dbf0ebf35,0xbf0e3f6d3e48bf80,0xbf7b3ec43f55bf35,0xbf55bec43f7b0000,0xbe48bf6d3f0e3f35,
0x3f553ec4bf7b8000,0x3e483f6dbf0ebf35,0xbf0e3f6d3e48bf80,0xbf7b3ec43f55bf35,0xbf55bec43f7b8000,0xbe48bf6d3f0e3f35,0x3f0ebf6dbe483f80,0x3f7bbec4bf553f35,
0x3f7fbe16bf6f3f0e,0x3f133f2cbf5fbe95,0xbdfbbf713f093f35,0x3f31bf5cbea13f7f,0xbf65be793f80be48,0xbe60bf673f1d3f22,0xbe893f80be2fbf6d,0xbf6a3f183f27bf62,
0xbd973f7dbeb8bf55,0xbf513f3e3efcbf75,0x3f7ebeacbf583f35,0x3f393f04bf73bdc9,0x3ee6bf78bcc93f7b,0x3f7abedbbf4a3f46,0xbf77bd493f7cbec4,0xbecfbf4e3f423ef1,
0x3d493f75bf04bf35,0xbf4e3f463edbbf7b,0xbf71bdc93f7dbec4,0xbe79bf623f2c3f0e,0xbf3ebef13f780000,0x3e16bf7f3eac3f55,0x3f67bf22bf183f6d,0x3f5c3e95bf803e48,
0xbf803e953f5cbf35,0xbf18bf223f673e48,0x3eacbf7f3e163f6d,0x3f78bef1bf3e3f55,0x3f2cbf62be793f80,0x3f7dbdc9bf713f0e,0x3edb3f46bf4ebec4,0xbf043f753d49bf7b,
0xbf7a3d493f73bf0e,0xbe89bf5c3f393ef1,0x3eb83f4ebf4abec4,0xbf273f673e2fbf7f,0x3f13bf71bd973f7b,0x3f7ebe16bf6a3f22,0xbf803e793f5fbf35,0xbee6bf3e3f583e95,
0x3e60bf803ea13f55,0x3f77bf04bf313f62,0xbf6f3f183f1dbf6d,0xbf42bedb3f7cbdc9,0x3f513eacbf7f3e48,0xbdfb3f7dbecfbf46,0x3cc9bf783efc3f35,0x3f65bf2cbf093f75,
0xbf463f553e95bf80,0xbf62be483f7fbec4,0x3dc9bf7b3ef13f35,0x3f75bf0ebf223f6d,0x3f223f0ebf750000,0xbef13f7bbdc9bf6d,0xbf7f3e483f62bf35,0xbe95bf553f463ec4,
0xbf22bf0e3f758000,0x3ef1bf7b3dc93f6d,0x3f7fbe48bf623f35,0x3e953f55bf46bec4,0xbf463f553e95bf80,0xbf62be483f7fbec4,0x3dc9bf7b3ef13f35,0x3f75bf0ebf223f6d,
0xbecfbf3e3f5f3e48,0x3f42bf5cbe603f7f,0xbe2f3f7dbee6bf35,0xbf7e3edb3f39bf62,0xbf803eac3f4abf55,0xbea1bf4e3f513e95,0x3f583e79bf7f3ec4,0xbe893f80beb8bf46,
0x3f6abf2cbefc3f7b,0x3f273f04bf7a3dc9,0xbf7c3e163f65bf35,0xbdfbbf673f313ef1,0xbcc9bf713f1d3f0e,0x3f73bf18bf133f75,0xbf093f78bd97bf6d,0xbf773d493f6fbf22,
0x3f78bdc9bf673f35,0xbd493f75bf18bf0e,0xbf7d3ef13f2cbf6d,0xbeacbf463f5c3e48,0x3f043f22bf710000,0xbf3e3f623e16bf7b,0xbf4ebe953f80bec4,0x3edbbf7f3e793f55,
0xbe793f7fbedbbf35,0xbf803e953f4ebf55,0xbe16bf623f3e3ec4,0x3f71bf22bf043f7b,0xbf5c3f463eacbf80,0xbf2cbef13f7dbe48,0x3f18bf753d493f6d,0x3f673dc9bf783f0e,
0xbf773f183f09bf7b,0xbeb8bf3e3f653dc9,0x3f7fbedbbf313f6d,0x3e2f3f5cbf4abe95,0xbf7e3e793f51bf55,0x3cc9bf713f273ef1,0x3f73bd49bf6a3f35,0xbe603f7dbefcbf22,
0xbe89bf4e3f583e48,0x3f6fbf2cbee63f7f,0x3d973f67bf39bec4,0xbf7c3f043f1dbf75,0x3dfbbf783f133f0e,0x3f80beacbf423f62,0xbea13f80becfbf35,0xbf7a3e163f5fbf46,
0x3f6dbf35bec43f80,0x3ec43f35bf6d0000,0xbf6d3f353ec4bf80,0xbec4bf353f6d0000,0x3f6dbf35bec43f80,0x3ec43f35bf6d0000,0xbf6d3f353ec4bf80,0xbec4bf353f6d0000,
0x3ec43f35bf6d8000,0xbf6d3f353ec4bf80,0xbec4bf353f6d8000,0x3f6dbf35bec43f80,0x3ec43f35bf6d8000,0xbf6d3f353ec4bf80,0xbec4bf353f6d8000,0x3f6dbf35bec43f80,
0xbf1d3f78be2fbf55,0xbf39beac3f7fbef1,0x3ee6bf803eb83f35,0x3f583e16bf773f22,0xbf5f3f4e3e60bf7b,0xbecfbf2c3f73bdc9,0x3f42bf67bcc93f6d,0x3f133f04bf7e3e95,
0xbf4abe793f7cbf0e,0x3f31bf713d973f62,0x3f653d49bf6f3f35,0xbf093f7dbe89bf46,0xbefcbf183f7abe48,0x3f6abf3ebea13f7f,0x3f273edbbf803ec4,0xbf513f5c3dfbbf75,
0x3f04bf7f3eac3f35,0x3f3e3e95bf7d3f0e,0xbf4e3f623d49bf6d,0xbedbbf223f78be48,0xbe79bf463f670000,0x3f80bef1bf183f7b,0xbe163f75bf2cbec4,0xbf713dc93f5cbf55,
0x3f5c3dc9bf713f35,0xbf2c3f75be16bf55,0xbf18bef13f80bec4,0x3f67bf46be793f7b,0x3f78bf22bedb3f80,0x3d493f62bf4ebe48,0xbf7d3e953f3ebf6d,0x3eacbf7f3f043f0e,
0xbf393f71bdfbbf55,0xbee6bf183f7cbe95,0x3e60bf783f273ec4,0x3f5f3d49bf6a3f46,0x3eb83f2cbf773e48,0xbf7f3f043f09bf7f,0xbf51be163f73bf35,0x3f4abf673cc93f62,
0xbf31beac3f7ebf0e,0x3f65bf4ebe2f3f75,0x3f7abe79bf423f6d,0xbefc3f80becfbf22,0xbf6f3f3e3e89bf7b,0xbd97bf5c3f583dc9,0x3f13bf7d3ea13f35,0x3f1d3edbbf803ef1,
0xbf7f3f0e3ef1bf80,0x3e95bf7b3f223ec4,0x3f463e48bf753f35,0xbf623f553dc9bf6d,0xbdc9bf553f620000,0x3f75be48bf463f6d,0xbf223f7bbe95bf35,0xbef1bf0e3f7fbec4,
0xbdc9bf553f628000,0x3f75be48bf463f6d,0xbf223f7bbe95bf35,0xbef1bf0e3f7fbec4,0x3f7fbf0ebef13f80,0xbe953f7bbf22bec4,0xbf46be483f75bf35,0x3f62bf55bdc93f6d,
0x3f7cbeacbf273f7b,0xbf1d3f7dbeb8bf22,0xbf313f78be89bf35,0xbea1bf2c3f7abe95,0xbf093f80bee6bf0e,0xbefcbf043f80bef1,0xbecfbf183f7ebec4,0x3f7fbedbbf133f7f,
0xbe2f3f71bf42be48,0xbf4abe163f6fbf46,0xbf39be793f77bf35,0x3f73bf3ebe603f75,0xbf58bd493f65bf55,0x3f5fbf5cbcc93f62,0x3f6abf4ebdfb3f6d,0xbd973f67bf51bdc9,
0xbf2cbe953f78bf35,0x3f7dbf22beac3f7b,0xbedb3f7fbf18bec4,0xbf04bef13f80bf0e,0xbd493f62bf5c0000,0xbf4ebdc93f67bf55,0x3f71bf46be163f6d,0xbe793f75bf3ebe48,
0x3f3ebf753e793f35,0x3e163f46bf713e48,0xbf673dc93f4ebf6d,0x3f5cbf623d493f55,0xbf803ef13f04bf80,0x3f18bf7f3edb3f0e,0x3eac3f22bf7d3ec4,0xbf783e953f2cbf7b,
0xbea13f78bf39be48,0xbf09bedb3f7ebf22,0xbf5f3d493f51bf6d,0x3f6fbf4ebd973f62,0x3f27bf7d3ecf3f0e,0x3e2f3f3ebf773e95,0x3f1d3eacbf7a3f35,0xbf803f043ee6bf7f,
0xbf733e793f31bf7b,0x3f58bf673dfb3f46,0x3efcbf803f133ec4,0x3eb83f18bf7f3ef1,0x3f423e16bf6a3f55,0xbf7c3f2c3e89bf75,0xbf4a3f71be60bf35,0x3cc9bf5c3f65bdc9,
0x3f7bbec4bf0e3f80,0xbf553f6dbe48bf35,0x3e48bf6d3f550000,0x3f0e3ec4bf7b3f35,0xbf7b3ec43f0ebf80,0x3f55bf6d3e483f35,0xbe483f6dbf550000,0xbf0ebec43f7bbf35,
0xbe483f6dbf558000,0xbf0ebec43f7bbf35,0x3f7bbec4bf0e3f80,0xbf553f6dbe48bf35,0x3e48bf6d3f558000,0x3f0e3ec4bf7b3f35,0xbf7b3ec43f0ebf80,0x3f55bf6d3e483f35,
0xbea1bf183f80bf0e,0x3f58bd49bf4a3f75,0x3f5fbf673e2f3f35,0xbeb83f78bf42bdc9,0xbd973f5cbf6a3e48,0xbf13beac3f77bf46,0xbf7e3f2c3e60bf6d,0x3f31bf7d3ee63ef1,
0x3f73bf4ebcc93f55,0xbf093f80bf1dbe95,0x3efc3edbbf7c3f35,0xbf6f3e793f27bf7f,0xbf7f3f043ecfbf7b,0x3f51bf713e893f22,0xbdfbbf3e3f7abec4,0x3f393e16bf653f62,
0xbf673f62be16bf35,0x3f04bf7f3f2c3e48,0x3d493f46bf783ec4,0xbf18be953f71bf55,0x3eacbf753f4e0000,0x3e793f22bf803f0e,0xbf3ebdc93f5cbf6d,0x3f7dbef1bedb3f7b,
0xbedbbef13f7dbf35,0x3f5cbdc9bf3e3f7b,0xbf803f223e79bf6d,0x3f4ebf753eac3f0e,0x3f71be95bf183f80,0xbf783f463d49bf55,0x3f2cbf7f3f043ec4,0xbe163f62bf673e48,
0x3e2f3f2cbf7f3f0e,0xbf1dbe793f6abf62,0xbf393f7dbefcbec4,0x3ea1bf713f58bdc9,0xbf7a3edb3ee6bf7b,0x3f77bf4e3cc93f46,0xbeb8bf043f7ebf35,0x3f423d49bf513f75,
0xbf7c3f3e3d97bf55,0x3f4abf783ecf3ef1,0xbf31be163f5fbf6d,0x3f73beacbf093f7f,0x3e60bf673f65be48,0x3e893f18bf803f22,0x3f6fbf5c3dfb3f35,0xbf273f80bf13be95,
0xbf623e483f22bf80,0x3f7fbf0ebe953f6d,0xbf753f55bdc9bf35,0x3f46bf7b3ef13ec4,0xbef13f7bbf460000,0x3dc9bf553f75bec4,0x3e953f0ebf7f3f35,0xbf22be483f62bf6d,
0x3ef1bf7b3f468000,0xbdc93f55bf753ec4,0xbe95bf0e3f7fbf35,0x3f223e48bf623f6d,0xbf623e483f22bf80,0x3f7fbf0ebe953f6d,0xbf753f55bdc9bf35,0x3f46bf7b3ef13ec4,
0xbf313f80bf1dbe48,0x3ee6bf783f51bdc9,0xbf7a3f4ebd97bf35,0x3f5fbf713eb83ef1,0x3ecf3edbbf773f55,0xbf27be163f58bf75,0xbe2f3f5cbf733ec4,0xbdfbbf2c3f80bf22,
0xbf39bd493f4abf7b,0x3f65be79bf133f7f,0xbe60bf183f7fbf35,0x3efc3eacbf6f3f62,0xbf6a3f67be89bf0e,0x3f42bf7d3f093e95,0xbf7c3f043ea1bf6d,0x3f7ebf3ebcc93f46,
0x3e163f22bf803f35,0xbeacbef13f78bf55,0x3f043e95bf673f6d,0xbf2cbdc93f4ebf7b,0xbf183f7fbf3e0000,0x3edbbf753f5cbe48,0xbe793f62bf713ec4,0x3d49bf463f7dbf0e,
0xbf7d3f46bd49bf35,0x3f71bf623e793f0e,0xbf5c3f75bedbbec4,0x3f3ebf7f3f183e48,0xbf4e3dc93f2cbf80,0x3f67be95bf043f7b,0xbf783ef13eacbf6d,0x3f80bf22be163f55,
0x3f1d3e16bf513f7b,0xbf31bd493f42bf7f,0x3ee63eacbf6a3f6d,0xbf09be793f5fbf75,0x3e893f04bf7a3f55,0xbeb8bedb3f73bf62,0x3d973f2cbf803f35,0xbe2fbf183f7ebf46,
0xbf4a3f7dbf13be48,0x3f39bf803f273dc9,0xbf653f71becfbec4,0x3f58bf783efc3e95,0xbf773f5cbe60bf0e,0x3f6fbf673ea13ef1,0xbf7f3f3ebcc9bf35,0x3f7cbf4e3dfb3f22,
0xbf3500003f353f80,0x3f350000bf35bf80,0xbf3500003f353f80,0x3f350000bf35bf80,0xbf3500003f353f80,0x3f350000bf35bf80,0xbf3500003f353f80,0x3f350000bf35bf80,
0xbf35bf80bf358000,0x3f353f803f358000,0xbf35bf80bf358000,0x3f353f803f358000,0xbf35bf80bf358000,0x3f353f803f358000,0xbf35bf80bf358000,0x3f353f803f358000,
0xbe893e79be603e48,0xbeb83eacbea13e95,0xbd973d49bcc90000,0xbe2f3e16bdfb3dc9,0xbf1d3f18bf133f0e,0xbf313f2cbf273f22,0xbee63edbbecf3ec4,0xbf093f04befc3ef1,
0xbf773f78bf7a3f7b,0xbf6f3f71bf733f75,0xbf7f3f80bf803f80,0xbf7c3f7dbf7e3f7f,0xbf4a3f4ebf513f55,0xbf393f3ebf423f46,0xbf653f67bf6a3f6d,0xbf583f5cbf5f3f62,
0x3f18bf223f2cbf35,0x3edbbef13f04bf0e,0x3e79be953eacbec4,0x3d49bdc93e16be48,0x3f7dbf7f3f80bf80,0x3f71bf753f78bf7b,0x3f5cbf623f67bf6d,0x3f3ebf463f4ebf55,
0xbf4e3f46bf3e3f35,0xbf673f62bf5c3f55,0xbf783f75bf713f6d,0xbf803f7fbf7d3f7b,0xbe163dc9bd498000,0xbeac3e95be793e48,0xbf043ef1bedb3ec4,0xbf2c3f22bf183f0e,
0x3f6abf713f77bf7b,0x3f42bf4e3f58bf62,0x3f7cbf783f73bf6d,0x3f7ebf803f80bf7f,0x3f39bf2c3f1dbf0e,0x3f65bf5c3f51bf46,0x3e60be163d970000,0x3efcbedb3eb8be95,
0xbecf3eacbe893e48,0xbf273f18bf093ef1,0x3e2fbe793ea1bec4,0xbdfb3d493cc9bdc9,0x3f31bf3e3f4abf55,0x3ee6bf043f13bf22,0x3f7abf7d3f7fbf80,0x3f5fbf673f6fbf75,
0xbf753f7bbf7f3f80,0xbf463f55bf623f6d,0xbef13f0ebf223f35,0xbdc93e48be953ec4,0x3e95be483dc90000,0x3f22bf0e3ef1bec4,0x3f62bf553f46bf35,0x3f7fbf7b3f75bf6d,
0x3e95be483dc98000,0x3f22bf0e3ef1bec4,0x3f62bf553f46bf35,0x3f7fbf7b3f75bf6d,0x3f75bf7b3f7fbf80,0x3f46bf553f62bf6d,0x3ef1bf0e3f22bf35,0x3dc9be483e95bec4,
0xbf7a3f71bf653f55,0xbf773f7dbf803f7f,0xbeb83e79bdfb0000,0xbf423f2cbf133ef1,0x3e2fbd49bd973e48,0x3f1dbf043ecfbe95,0xbf393f4ebf5f3f6d,0xbea13edbbf093f22,
0xbe603eacbee63f0e,0x3e89be163cc93dc9,0xbf6f3f78bf7e3f80,0xbf273f3ebf513f62,0x3f7cbf803f7fbf7b,0x3f4abf5c3f6abf75,0x3f31bf183efcbec4,0x3f73bf673f58bf46,
0xbf713f62bf4e3f35,0xbf783f7fbf803f7b,0xbf2c3f46bf5c3f6d,0xbe163e95bedb3f0e,0x3f67bf753f7dbf80,0x3f04bf223f3ebf55,0xbd49bdc93e79bec4,0xbf183ef1beac3e48,
0xbeac3ef1bf183f35,0x3e79bdc9bd493e48,0x3f3ebf223f04bec4,0x3f7dbf753f67bf55,0xbedb3e95be168000,0xbf5c3f46bf2c3f0e,0xbf803f7fbf783f6d,0xbf4e3f62bf713f7b,
0xbf7f3f78bf6a3f55,0xbf513f67bf773f7f,0xbdfbbd493e60bec4,0xbf393f18bee63e95,0x3f73bf7d3f80bf7b,0x3f09bf2c3f4abf62,0x3efcbeac3e2f0000,0x3f6fbf5c3f42bf22,
0xbd973e79becf3f0e,0x3f13bedb3e89bdc9,0xbf7e3f80bf7a3f6d,0xbf313f4ebf653f75,0xbea13e163cc9be48,0xbf583f3ebf1d3ef1,0x3f5fbf713f7cbf80,0x3eb8bf043f27bf46,
0xbf553f6dbf7b3f80,0xbe483ec4bf0e3f35,0x3f0ebec43e480000,0x3f7bbf6d3f55bf35,0x3f55bf6d3f7bbf80,0x3e48bec43f0ebf35,0xbf0e3ec4be480000,0xbf7b3f6dbf553f35,
0x3f0ebec43e488000,0x3f7bbf6d3f55bf35,0x3f55bf6d3f7bbf80,0x3e48bec43f0ebf35,0xbf0e3ec4be488000,0xbf7b3f6dbf553f35,0xbf553f6dbf7b3f80,0xbe483ec4bf0e3f35,
0xbf273f4ebf6a3f7b,0x3e2f3d49be893ef1,0xbf1d3edbbe600000,0xbf803f78bf653f46,0x3ea1bf043f31bf55,0xbf093eacbdfbbdc9,0x3f5fbf3e3f13bec4,0x3f6fbf7d3f7fbf75,
0x3f42bf183ecfbe48,0x3f7cbf803f77bf62,0xbf4a3f67bf7a3f80,0xbcc93e79bee63f22,0xbf733f5cbf393f0e,0xbf583f71bf7e3f7f,0x3efcbf2c3f51bf6d,0xbeb83e163d97be95,
0xbd493e95bf043f35,0x3f4ebf223edbbe48,0x3f71bf7f3f7dbf6d,0x3e79bef13f2cbf55,0x3f3ebf623f78bf80,0xbe16bdc93eacbf0e,0xbf673f46bf183ec4,0xbf5c3f75bf803f7b,
0x3f80bf753f5cbf35,0x3f18bf463f67bf7b,0xbeac3dc93e16bec4,0xbf783f62bf3e3f0e,0xbf2c3ef1be798000,0xbf7d3f7fbf713f55,0xbedb3f22bf4e3f6d,0x3f04be953d493e48,
0x3f58bf2c3ee6be48,0x3f5fbf783f80bf75,0xbf6a3f7dbf7e3f6d,0xbd973eacbf133f46,0x3e2fbedb3f27bf55,0xbf4a3f18beb83dc9,0x3f39bf043e890000,0x3f73bf803f7abf62,
0x3f09bf3e3f65bf7b,0xbefc3e793cc9be95,0x3ecfbe16bdfb3ec4,0x3f7fbf713f51bf22,0xbf7c3f67bf423f0e,0xbf1d3f4ebf6f3f7f,0x3f31bf5c3f77bf80,0xbea13d493e60bef1,
0xbf223f55bf753f80,0x3ef1be48bdc93ec4,0x3f7fbf7b3f62bf35,0x3e95bf0e3f46bf6d,0xbf463f0ebe950000,0xbf623f7bbf7f3f6d,0x3dc93e48bef13f35,0x3f75bf553f22bec4,
0x3f46bf0e3e958000,0x3f62bf7b3f7fbf6d,0xbdc9be483ef1bf35,0xbf753f55bf223ec4,0xbf223f55bf753f80,0x3ef1be48bdc93ec4,0x3f7fbf7b3f62bf35,0x3e95bf0e3f46bf6d,
0x3eb8bd49be893f0e,0x3f7fbf783f58bf22,0xbf513f18bea10000,0xbf4a3f71bf803f75,0xbf393f67bf7e3f7b,0x3ee6be16be2f3ef1,0x3e60bf043f42bf6d,0xbf5f3f2cbecf3dc9,
0x3f6fbf803f77bf55,0xbd97be793f09bf46,0xbf133f4ebf733f80,0x3f1dbeac3cc93e95,0x3f31bedb3dfb3e48,0x3f65bf7d3f7cbf62,0xbf7a3f5cbf273ec4,0xbefc3f3ebf6a3f7f,
0x3f78bf7f3f67bf35,0xbd49be953f18bf55,0xbf7d3f62bf2c3ec4,0xbeac3f22bf5c3f7b,0x3f04bf463f71bf80,0xbf3e3ef1be16be48,0xbf4e3f75bf803f6d,0x3edbbdc9be793f0e,
0xbe79bdc93edbbf35,0xbf803f75bf4e3f0e,0xbe163ef1bf3e3f6d,0x3f71bf463f04be48,0xbf5c3f22beac8000,0xbf2c3f62bf7d3f7b,0x3f18be95bd493ec4,0x3f67bf7f3f78bf55,
0xbefc3e163e60bf0e,0xbf6a3f80bf733f46,0x3f27beacbcc93ec4,0x3f51bf783f7ebf62,0xbf4a3f04be2fbe48,0xbf313f67bf7f3f75,0x3f65bf2c3eb80000,0x3f09bf4e3f77bf7f,
0xbf5f3f7dbf7a3f55,0x3ecfbd49bea13f22,0x3f42bf713f80bf6d,0xbf133e793dfbbef1,0xbf1d3f5cbf7c3f7b,0x3f39bedb3d973e95,0x3ee6bf3e3f6fbf80,0xbf583f18be89bdc9,
0xbec43f35bf6d3f80,0x3f6dbf353ec40000,0x3ec4bf353f6dbf80,0xbf6d3f35bec40000,0xbec43f35bf6d3f80,0x3f6dbf353ec40000,0x3ec4bf353f6dbf80,0xbf6d3f35bec40000,
0x3f6dbf353ec48000,0x3ec4bf353f6dbf80,0xbf6d3f35bec48000,0xbec43f35bf6d3f80,0x3f6dbf353ec48000,0x3ec4bf353f6dbf80,0xbf6d3f35bec48000,0xbec43f35bf6d3f80,
0x3f7ebf5c3f13be48,0x3cc9bedb3f42bf75,0xbf733f3ebecf0000,0xbe603f18bf5f3f7f,0x3f77bf7d3f58bf0e,0xbeb8bd493ee6bf46,0xbf7f3f71bf393ec4,0x3e2f3e79bf1d3f62,
0x3dfbbf043f51bf7b,0xbf803f67bf273e95,0xbea13f2cbf6a3f80,0x3f7abf4e3efcbdc9,0xbe89be163f09bf55,0xbf6f3f80bf653f22,0x3d973eacbf313f6d,0x3f7cbf783f4abef1,
0xbf043dc93eacbf35,0xbf3e3f75bf7d3f55,0x3f4ebef13d493ec4,0x3edbbf463f78bf7b,0x3e79bf223f67bf80,0xbf803f62bf183e48,0x3e163e95bf2c3f6d,0x3f71bf7f3f5cbf0e,
0xbf5c3f7fbf713f35,0x3f2cbe95be163f0e,0x3f18bf623f80bf6d,0xbf673f22be79be48,0xbf783f46bedb8000,0xbd493ef1bf4e3f7b,0x3f7dbf753f3ebec4,0xbeacbdc93f04bf55,
0x3cc93edbbf4a3f7b,0x3f73bf7d3f51bef1,0x3f09bf5c3f7fbf6d,0xbf773f3ebeb8bdc9,0xbf6a3f80bf5f3f0e,0x3f27be79be603f22,0x3f7cbf4e3ee60000,0xbdfbbeac3f39bf75,
0x3f80bf673f1dbe48,0xbea1be163f13bf62,0xbf583f04bd97bec4,0xbe893f2cbf6f3f7f,0x3ecf3d49befc3f55,0x3f42bf783f7abf46,0x3e2fbf183f65bf80,0xbf7e3f71bf313e95,
0xbdc93f0ebf623f80,0x3f75bf7b3f46bec4,0xbf223e483e95bf35,0xbef13f55bf7f3f6d,0x3f7fbf553ef10000,0xbe95be483f22bf6d,0xbf463f7bbf753f35,0x3f62bf0e3dc93ec4,
0x3f7fbf553ef18000,0xbe95be483f22bf6d,0xbf463f7bbf753f35,0x3f62bf0e3dc93ec4,0x3dc9bf0e3f62bf80,0xbf753f7bbf463ec4,0x3f22be48be953f35,0x3ef1bf553f7fbf6d,
0x3f13bf673f7fbf55,0xbf7e3f4ebecfbdc9,0xbf803f5cbefc0000,0x3ee63d49bf093f62,0xbf7a3f3ebea1be48,0x3e893e79bf313f75,0x3eb83e16bf1d3f6d,0x3f27bf713f7cbf46,
0xbf513edb3d97bf0e,0xbdfb3f18bf6a3f7f,0xbcc93f04bf5f3f80,0x3f65bf803f58bef1,0xbe603f2cbf733f7b,0x3f77bf783f39be95,0x3f6fbf7d3f4abec4,0xbf423eac3e2fbf22,
0xbf2c3f75bf783f35,0x3f7dbf463eac3e48,0xbedbbdc93f18bf6d,0xbf043f62bf803f55,0xbd49bef13f5cbf80,0xbf4e3f7fbf673f0e,0x3f71bf223e163ec4,0xbe79be953f3ebf7b,
0x3f3ebe95be793f35,0x3e16bf223f71bf7b,0xbf673f7fbf4e3ec4,0x3f5cbef1bd493f0e,0xbf803f62bf048000,0x3f18bdc9bedb3f55,0x3eacbf463f7dbf6d,0xbf783f75bf2c3e48,
0x3ee6bf5c3f80bf55,0xbf7a3f71bf1d3dc9,0xbf773f2cbe2fbec4,0x3ecf3e16bf273f75,0xbd973f18bf6f3f7b,0x3f51bf803f5fbef1,0x3f7ebf673f090000,0xbf393e793ea1bf46,
0xbf653f043cc9bf0e,0x3e603eacbf4a3f7f,0xbe893f3ebf7c3f6d,0x3f6abf7d3f42be95,0x3f7fbf4e3eb83e48,0xbf133d493efcbf62,0xbdfbbedb3f58bf80,0xbf313f78bf733f22,
0x3e483ec4bf553f80,0x3f0ebf6d3f7bbf35,0xbf7b3f6dbf0e0000,0x3f55bec4be483f35,0xbe48bec43f55bf80,0xbf0e3f6dbf7b3f35,0x3f7bbf6d3f0e0000,0xbf553ec43e48bf35,
0x3f7bbf6d3f0e8000,0xbf553ec43e48bf35,0x3e483ec4bf553f80,0x3f0ebf6d3f7bbf35,0xbf7b3f6dbf0e8000,0x3f55bec4be483f35,0xbe48bec43f55bf80,0xbf0e3f6dbf7b3f35,
0xbee6be163f31bf7b,0xbe603f3ebf7e3f62,0xbf773f71bf130000,0x3f6abf04bd973f22,0x3f42be79beb83f55,0xbe2fbedb3f5fbf7f,0x3f4abf803f58bec4,0xbf803f4ebea1be95,
0xbf653f7dbf393e48,0x3f7abf2c3dfb3ef1,0x3e893eacbf513f80,0x3ecfbf5c3f7fbf46,0x3f27bf783f6fbf0e,0xbf7c3f67befcbdc9,0xbf1d3d493f09bf6d,0xbcc93f18bf733f75,
0x3f67bef1be163f35,0xbf04bdc93f2cbf7b,0xbd493f22bf783f6d,0x3f18bf753f71bf0e,0xbeacbe953f4ebf80,0xbe793f46bf803f55,0x3f3ebf7f3f5cbec4,0xbf7d3f62bedbbe48,
0x3edbbf623f7dbf35,0xbf5c3f7fbf3e3e48,0x3f80bf463e793ec4,0xbf4e3e953eacbf55,0xbf713f75bf188000,0x3f78bf223d493f0e,0xbf2c3dc93f04bf6d,0x3e163ef1bf673f7b,
0xbf513f80bf423e48,0x3f7ebf5c3eb83e95,0x3cc93f18bf773f6d,0x3ee6bf673f7abf22,0x3f58beacbea13f55,0xbefcbe163f39bf7f,0x3f6abf783f1d0000,0xbf7f3f3ebe2fbef1,
0x3f133d49bf273f7b,0xbdfbbf043f6fbf75,0x3f80bf4e3e893ec4,0xbf653edb3e60bf46,0x3f09bf713f73bf0e,0xbf5f3f7dbf313dc9,0xbecfbe793f4abf80,0xbd973f2cbf7c3f62,
0x3ef13e48bf463f80,0xbdc9bf0e3f75bf6d,0xbe953f55bf7f3f35,0x3f22bf7b3f62bec4,0xbf623f7bbf220000,0x3f7fbf553e953ec4,0xbf753f0e3dc9bf35,0x3f46be48bef13f6d,
0x3f62bf7b3f228000,0xbf7f3f55be95bec4,0x3f75bf0ebdc93f35,0xbf463e483ef1bf6d,0x3ef13e48bf463f80,0xbdc9bf0e3f75bf6d,0xbe953f55bf7f3f35,0x3f22bf7b3f62bec4,
0xbf803f3ebdfbbf0e,0x3f73bf04be2f3f46,0xbf583f7dbf270000,0x3f77bf673ecf3e95,0xbeb8beac3f5fbf7b,0x3d973f18bf7a3f62,0xbf513e793ee6bf6d,0x3f1d3d49bf313f7f,
0xbcc93f2cbf7e3f55,0x3ea1bf5c3f7cbf22,0x3f093e16bf423f80,0xbe89bedb3f6abf75,0xbf6f3f71befcbe48,0x3f7fbf4e3e603ef1,0xbf133f78bf653ec4,0x3f4abf803f39bdc9,
0x3e16bf463f80bf35,0xbeac3f62bf783f0e,0x3f04bf753f67bec4,0xbf2c3f7fbf4e3e48,0xbf18bdc93f3ebf80,0x3edb3e95bf5c3f7b,0xbe79bef13f71bf6d,0x3d493f22bf7d3f55,
0xbf7d3f223d49bf35,0x3f71bef1be793f55,0xbf5c3e953edbbf6d,0x3f3ebdc9bf183f7b,0xbf4e3f7fbf2c8000,0x3f67bf753f043e48,0xbf783f62beacbec4,0x3f80bf463e163f0e,
0x3f7ebf4e3e2f3f0e,0xbf803f3ebd97bf22,0x3f73bf673eb83ec4,0xbf7a3f5cbe89bef1,0x3f5fbf783f093e48,0xbf6a3f71bee6be95,0x3f42bf803f310000,0xbf513f7dbf1dbdc9,
0xbdfbbf183f7cbf55,0x3cc93f2cbf7f3f46,0xbea1bedb3f6fbf6d,0x3e603f04bf773f62,0xbefcbe793f58bf7b,0x3ecf3eacbf653f75,0xbf27bd493f39bf80,0x3f133e16bf4a3f7f,
0xbf3500003f353f80,0x3f350000bf35bf80,0xbf3500003f353f80,0x3f350000bf35bf80,0xbf3500003f353f80,0x3f350000bf35bf80,0xbf3500003f353f80,0x3f350000bf35bf80,
0xbf35bf80bf358000,0x3f353f803f358000,0xbf35bf80bf358000,0x3f353f803f358000,0xbf35bf80bf358000,0x3f353f803f358000,0xbf35bf80bf358000,0x3f353f803f358000,
0xbf5f3f5cbf583f55,0xbf6a3f67bf653f62,0xbf423f3ebf393f35,0xbf513f4ebf4a3f46,0xbf7e3f7dbf7c3f7b,0xbf803f80bf7f3f7f,0xbf733f71bf6f3f6d,0xbf7a3f78bf773f75,
0xbefc3f04bf093f0e,0xbecf3edbbee63ef1,0xbf273f2cbf313f35,0xbf133f18bf1d3f22,0xbdfb3e16be2f3e48,0xbcc93d49bd973dc9,0xbea13eacbeb83ec4,0xbe603e79be893e95,
0xbf4e3f46bf3e3f35,0xbf673f62bf5c3f55,0xbf783f75bf713f6d,0xbf803f7fbf7d3f7b,0xbe163dc9bd490000,0xbeac3e95be793e48,0xbf043ef1bedb3ec4,0xbf2c3f22bf183f0e,
0xbf183f22bf2c3f35,0xbedb3ef1bf043f0e,0xbe793e95beac3ec4,0xbd493dc9be163e48,0xbf7d3f7fbf803f80,0xbf713f75bf783f7b,0xbf5c3f62bf673f6d,0xbf3e3f46bf4e3f55,
0xbf6f3f67bf5f3f55,0xbf7f3f7dbf7a3f75,0xbf133f04bee63ec4,0xbf4a3f3ebf313f22,0xbcc9bd493dfbbe48,0xbea13e79be2f3dc9,0x3f09bf183f27bf35,0x3e89beac3ecfbef1,
0xbeb83edbbefc3f0e,0xbd973e16be603e95,0xbf513f5cbf653f6d,0xbf1d3f2cbf393f46,0xbf803f80bf7e3f7b,0xbf733f78bf7c3f7f,0xbf583f4ebf423f35,0xbf773f71bf6a3f62,
0x3f75bf7b3f7fbf80,0x3f46bf553f62bf6d,0x3ef1bf0e3f22bf35,0x3dc9be483e95bec4,0xbe953e48bdc90000,0xbf223f0ebef13ec4,0xbf623f55bf463f35,0xbf7f3f7bbf753f6d,
0xbe953e48bdc98000,0xbf223f0ebef13ec4,0xbf623f55bf463f35,0xbf7f3f7bbf753f6d,0xbf753f7bbf7f3f80,0xbf463f55bf623f6d,0xbef13f0ebf223f35,0xbdc93e48be953ec4,
0x3f58bf673f73bf7b,0x3efcbf183f31bf46,0x3f6abf5c3f4abf35,0x3f7fbf803f7cbf75,0xbf513f3ebf273f0e,0xbf7e3f78bf6f3f62,0x3cc9be163e89bec4,0xbee63eacbe603dc9,
0xbf093edbbea13e48,0xbf5f3f4ebf393f22,0x3ecfbf043f1dbf35,0xbd97bd493e2fbe95,0xbf133f2cbf423f55,0xbdfb3e79beb83ef1,0xbf803f7dbf773f6d,0xbf653f71bf7a3f7f,
0x3eacbef13f18bf35,0xbe793dc93d49be48,0xbf3e3f22bf043ec4,0xbf7d3f75bf673f55,0x3edbbe953e160000,0x3f5cbf463f2cbf0e,0x3f80bf7f3f78bf6d,0x3f4ebf623f71bf7b,
0xbf713f62bf4e3f35,0xbf783f7fbf803f7b,0xbf2c3f46bf5c3f6d,0xbe163e95bedb3f0e,0x3f67bf753f7dbf80,0x3f04bf223f3ebf55,0xbd49bdc93e79bec4,0xbf183ef1beac3e48,
0xbf273f04beb83e48,0xbf7c3f71bf5f3f46,0x3f1dbf3e3f58bf6d,0xbcc9be163ea1bef1,0x3f65bf4e3f31bf0e,0x3f7abf803f7ebf75,0xbe893edbbf133f35,0x3ecfbe793d973dc9,
0xbf423f5cbf6f3f7b,0xbe2f3eacbefc3f22,0xbf4a3f2cbf093ec4,0xbf803f7dbf733f62,0x3ee6bf183f39bf55,0xbe603d493dfbbe95,0x3f77bf673f51bf35,0x3f6abf783f7fbf7f,
0xbf553f6dbf7b3f80,0xbe483ec4bf0e3f35,0x3f0ebec43e480000,0x3f7bbf6d3f55bf35,0x3f55bf6d3f7bbf80,0x3e48bec43f0ebf35,0xbf0e3ec4be480000,0xbf7b3f6dbf553f35,
0x3f0ebec43e488000,0x3f7bbf6d3f55bf35,0x3f55bf6d3f7bbf80,0x3e48bec43f0ebf35,0xbf0e3ec4be488000,0xbf7b3f6dbf553f35,0xbf553f6dbf7b3f80,0xbe483ec4bf0e3f35,
0x3d973e16beb83f0e,0x3f51bf2c3efcbe95,0xbf7e3f71bf583f35,0xbf393f5cbf733f7f,0xbee63e79bcc9be48,0xbf7a3f67bf4a3f22,0x3f77bf803f7cbf6d,0x3ecfbf183f42bf62,
0x3f7fbf7d3f6fbf55,0x3f13bf3e3f5fbf75,0xbdfb3eacbf093f35,0x3f31bf043ea1bdc9,0xbf653f78bf803f7b,0xbe603edbbf1d3f46,0xbe893d493e2fbec4,0xbf6a3f4ebf273ef1,
0x3f80bf753f5cbf35,0x3f18bf463f67bf7b,0xbeac3dc93e16bec4,0xbf783f62bf3e3f0e,0xbf2c3ef1be790000,0xbf7d3f7fbf713f55,0xbedb3f22bf4e3f6d,0x3f04be953d493e48,
0x3d49be953f04bf35,0xbf4e3f22bedb3e48,0xbf713f7fbf7d3f6d,0xbe793ef1bf2c3f55,0xbf3e3f62bf783f80,0x3e163dc9beac3f0e,0x3f67bf463f18bec4,0x3f5cbf753f80bf7b,
0xbe60bd493ea1bf0e,0xbf773f5cbf313ef1,0x3f6fbf4e3f1dbec4,0x3f42bf673f7cbf7f,0xbf513f71bf7f3f7b,0x3dfb3e16becf3f22,0xbcc9be793efcbf35,0xbf653f3ebf093e95,
0xbf7a3f80bf733f55,0xbe893f04bf393f62,0x3eb8bf183f4abf6d,0xbf273edbbe2fbdc9,0x3f13beac3d973e48,0x3f7ebf7d3f6abf46,0xbf803f78bf5f3f35,0xbee63f2cbf583f75,
0x3f22bf553f75bf80,0xbef13e483dc9bec4,0xbf7f3f7bbf623f35,0xbe953f0ebf463f6d,0x3f46bf0e3e950000,0x3f62bf7b3f7fbf6d,0xbdc9be483ef1bf35,0xbf753f55bf223ec4,
0xbf463f0ebe958000,0xbf623f7bbf7f3f6d,0x3dc93e48bef13f35,0x3f75bf553f22bec4,0x3f22bf553f75bf80,0xbef13e483dc9bec4,0xbf7f3f7bbf623f35,0xbe953f0ebf463f6d,
0xbf6a3f3ebefc3e48,0xbf273f5cbf7a3f7f,0x3f7cbf7d3f65bf35,0x3dfbbedb3f31bf62,0x3cc9beac3f1dbf55,0xbf733f4ebf133e95,0x3f09be79bd973ec4,0x3f77bf803f6fbf46,
0xbecf3f2cbf5f3f7b,0x3f42bf043e603dc9,0xbe2fbe163ee6bf35,0xbf7e3f67bf393ef1,0xbf803f71bf4a3f0e,0xbea13f18bf513f75,0x3f58bf783f7fbf6d,0xbe89bd493eb8bf22,
0x3e793dc9bedb3f35,0x3f80bf753f4ebf0e,0x3e16bef13f3ebf6d,0xbf713f46bf043e48,0x3f5cbf223eac0000,0x3f2cbf623f7dbf7b,0xbf183e953d49bec4,0xbf673f7fbf783f55,
0x3f78bf7f3f67bf35,0xbd49be953f18bf55,0xbf7d3f62bf2c3ec4,0xbeac3f22bf5c3f7b,0x3f04bf463f71bf80,0xbf3e3ef1be16be48,0xbf4e3f75bf803f6d,0x3edbbdc9be793f0e,
0x3e89bf183f58bf7b,0xbf6f3f3ebee63dc9,0xbd973edbbf393f6d,0x3f7cbf5c3f1dbe95,0xbdfbbe793f13bf55,0xbf803f71bf423ef1,0x3ea13d49becf3f35,0x3f7abf7d3f5fbf22,
0xbf773f4ebf093e48,0xbeb83f2cbf653f7f,0x3f7fbf673f31bec4,0x3e2fbf043f4abf75,0xbf7e3f78bf513f0e,0x3cc93eacbf273f62,0x3f73bf803f6abf35,0xbe60be163efcbf46,
0xbec43f35bf6d3f80,0x3f6dbf353ec40000,0x3ec4bf353f6dbf80,0xbf6d3f35bec40000,0xbec43f35bf6d3f80,0x3f6dbf353ec40000,0x3ec4bf353f6dbf80,0xbf6d3f35bec40000,
0x3f6dbf353ec48000,0x3ec4bf353f6dbf80,0xbf6d3f35bec48000,0xbec43f35bf6d3f80,0x3f6dbf353ec48000,0x3ec4bf353f6dbf80,0xbf6d3f35bec48000,0xbec43f35bf6d3f80,
0x3f4abf783f7cbf55,0xbf313eac3d97bef1,0xbf653f80bf6f3f35,0x3f09be16be893f22,0x3efcbf4e3f7abf7b,0xbf6a3f2cbea1bdc9,0xbf273f67bf803f6d,0x3f51bf043dfb3e95,
0xbf1d3e793e2fbf0e,0xbf393f71bf7f3f62,0x3ee6bd49beb83f35,0x3f58bf7d3f77bf46,0xbf5f3f18be60be48,0xbecf3f3ebf733f7f,0x3f42bedb3cc93ec4,0x3f13bf5c3f7ebf75,
0xbf5c3f7fbf713f35,0x3f2cbe95be163f0e,0x3f18bf623f80bf6d,0xbf673f22be79be48,0xbf783f46bedb0000,0xbd493ef1bf4e3f7b,0x3f7dbf753f3ebec4,0xbeacbdc93f04bf55,
0x3f04bdc9beac3f35,0x3f3ebf753f7dbf55,0xbf4e3ef1bd49bec4,0xbedb3f46bf783f7b,0xbe793f22bf673f80,0x3f80bf623f18be48,0xbe16be953f2cbf6d,0xbf713f7fbf5c3f0e,
0x3f31bf713f7ebf55,0xbf653f18be2fbe95,0xbf7a3f78bf423ec4,0x3efcbd49becf3f46,0x3f6fbf2c3e893e48,0x3d97bf043f58bf7f,0xbf133e163ea1bf35,0xbf1d3f67bf803f62,
0xbf393eac3dfbbf0e,0xbee63f4ebf7c3f75,0x3e603e79bf273f6d,0x3f5fbf803f6abf22,0x3eb8bf3e3f77bf7b,0xbf7f3f5cbf093dc9,0xbf513f7dbf733f35,0x3f4abedbbcc93ef1,
0x3dc9bf0e3f62bf80,0xbf753f7bbf463ec4,0x3f22be48be953f35,0x3ef1bf553f7fbf6d,0xbf7f3f55bef10000,0x3e953e48bf223f6d,0x3f46bf7b3f75bf35,0xbf623f0ebdc9bec4,
0xbf7f3f55bef18000,0x3e953e48bf223f6d,0x3f46bf7b3f75bf35,0xbf623f0ebdc9bec4,0xbdc93f0ebf623f80,0x3f75bf7b3f46bec4,0xbf223e483e95bf35,0xbef13f55bf7f3f6d,
0x3e2f3eacbf423f7b,0x3f4abf7d3f6fbf22,0x3f39bf783f77bf35,0xbf733f2cbe60be95,0x3f58bf803f65bf0e,0xbf5f3f04bcc9bef1,0xbf6a3f18bdfbbec4,0x3d973edbbf513f7f,
0x3f7cbf713f27be48,0xbf1d3e163eb8bf46,0xbf313e793e89bf35,0xbea13f3ebf7a3f75,0xbf093d493ee6bf55,0xbefc3f5cbf803f62,0xbecf3f4ebf7e3f6d,0x3f7fbf673f13bdc9,
0xbf3e3e953e79bf35,0xbe163f22bf713f7b,0x3f67bf7f3f4ebec4,0xbf5c3ef13d49bf0e,0x3f80bf623f040000,0xbf183dc93edbbf55,0xbeac3f46bf7d3f6d,0x3f78bf753f2cbe48,
0xbf2c3f75bf783f35,0x3f7dbf463eac3e48,0xbedbbdc93f18bf6d,0xbf043f62bf803f55,0xbd49bef13f5cbf80,0xbf4e3f7fbf673f0e,0x3f71bf223e163ec4,0xbe79be953f3ebf7b,
0x3f73bf783f31be48,0xbf583edb3dfbbf22,0xbefcbd493f13bf6d,0xbeb83f4ebf7f3f62,0xbf423f7dbf6a3f0e,0x3f7cbf3e3e893e95,0x3f4abeacbe603f35,0xbcc9bf043f65bf7f,
0xbea1be793f39bf7b,0xbf093f67bf7e3f46,0xbf5f3f80bf513ec4,0x3f6fbf183d973ef1,0x3f27be16becf3f55,0x3e2fbf2c3f77bf75,0x3f1dbf713f7abf35,0xbf803f5cbee6bdc9,
0x3e483ec4bf553f80,0x3f0ebf6d3f7bbf35,0xbf7b3f6dbf0e0000,0x3f55bec4be483f35,0xbe48bec43f55bf80,0xbf0e3f6dbf7b3f35,0x3f7bbf6d3f0e0000,0xbf553ec43e48bf35,
0x3f7bbf6d3f0e8000,0xbf553ec43e48bf35,0x3e483ec4bf553f80,0x3f0ebf6d3f7bbf35,0xbf7b3f6dbf0e8000,0x3f55bec4be483f35,0xbe48bec43f55bf80,0xbf0e3f6dbf7b3f35,
0xbf733f18bcc9bf0e,0x3f093d49bf1d3f75,0xbefc3f67bf7c3f35,0x3f6fbf783f27bdc9,0x3f7fbf5c3ecf3e48,0xbf513eac3e89bf46,0x3dfbbf2c3f7abf6d,0xbf393f7dbf653ef1,
0xbea13f4ebf803f55,0x3f58bf803f4abe95,0x3f5fbedbbe2f3f35,0xbeb8be793f42bf7f,0xbd97bf043f6abf7b,0xbf133f71bf773f22,0xbf7e3f3ebe60bec4,0x3f31be16bee63f62,
0x3edbbf623f7dbf35,0xbf5c3f7fbf3e3e48,0x3f80bf463e793ec4,0xbf4e3e953eacbf55,0xbf713f75bf180000,0x3f78bf223d493f0e,0xbf2c3dc93f04bf6d,0x3e163ef1bf673f7b,
0xbf673ef13e16bf35,0x3f043dc9bf2c3f7b,0x3d49bf223f78bf6d,0xbf183f75bf713f0e,0x3eac3e95bf4e3f80,0x3e79bf463f80bf55,0xbf3e3f7fbf5c3ec4,0x3f7dbf623edb3e48,
0x3f7cbf2c3d973f0e,0xbf4a3e793ecfbf62,0x3f31bf7d3f5fbec4,0xbf733f71bf09bdc9,0xbe60bedb3f65bf7b,0xbe893f4ebf803f46,0xbf6f3f043dfbbf35,0x3f27bd49bf133f75,
0x3e2fbf3e3f7fbf55,0xbf1d3f78bf6a3ef1,0xbf393e163efcbf6d,0x3ea13eacbf583f7f,0xbf7a3f67bee6be48,0x3f77bf18bcc93f22,0xbeb83f5cbf7e3f35,0x3f42bf803f51be95,
0xbef1be483f46bf80,0x3dc93f0ebf753f6d,0x3e95bf553f7fbf35,0xbf223f7bbf623ec4,0x3f62bf7b3f220000,0xbf7f3f55be95bec4,0x3f75bf0ebdc93f35,0xbf463e483ef1bf6d,
0xbf623f7bbf228000,0x3f7fbf553e953ec4,0xbf753f0e3dc9bf35,0x3f46be48bef13f6d,0xbef1be483f46bf80,0x3dc93f0ebf753f6d,0x3e95bf553f7fbf35,0xbf223f7bbf623ec4,
0x3f39bf803f4abe48,0xbf653f78bf13bdc9,0x3e60bf4e3f7fbf35,0xbefc3f71bf6f3ef1,0x3f6abedbbe893f55,0xbf423e163f09bf75,0x3f7cbf5c3ea13ec4,0xbf7e3f2cbcc9bf22,
0xbf313d493f1dbf7b,0x3ee63e79bf513f7f,0xbf7a3f183d97bf35,0x3f5fbeacbeb83f62,0x3ecfbf673f77bf0e,0xbf273f7dbf583e95,0xbe2fbf043f73bf6d,0xbdfb3f3ebf803f46,
0x3f7dbf22bd493f35,0xbf713ef13e79bf55,0x3f5cbe95bedb3f6d,0xbf3e3dc93f18bf7b,0x3f4ebf7f3f2c0000,0xbf673f75bf04be48,0x3f78bf623eac3ec4,0xbf803f46be16bf0e,
0x3e16bf463f80bf35,0xbeac3f62bf783f0e,0x3f04bf753f67bec4,0xbf2c3f7fbf4e3e48,0xbf18bdc93f3ebf80,0x3edb3e95bf5c3f7b,0xbe79bef13f71bf6d,0x3d493f22bf7d3f55,
0x3f4abe16bf133f7b,0xbf393d493f27bf7f,0x3f65beacbecf3f6d,0xbf583e793efcbf75,0x3f77bf04be603f55,0xbf6f3edb3ea1bf62,0x3f7fbf2cbcc93f35,0xbf7c3f183dfbbf46,
0x3f1dbf7d3f51be48,0xbf313f80bf423dc9,0x3ee6bf713f6abec4,0xbf093f78bf5f3e95,0x3e89bf5c3f7abf0e,0xbeb83f67bf733ef1,0x3d97bf3e3f80bf35,0xbe2f3f4ebf7e3f22,
0x3f350000bf353f80,0xbf3500003f35bf80,0x3f350000bf353f80,0xbf3500003f35bf80,0x3f350000bf353f80,0xbf3500003f35bf80,0x3f350000bf353f80,0xbf3500003f35bf80,
0xbf353f80bf358000,0x3f35bf803f358000,0xbf353f80bf358000,0x3f35bf803f358000,0xbf353f80bf358000,0x3f35bf803f358000,0xbf353f80bf358000,0x3f35bf803f358000,
0x3f77be79bf7a3e48,0x3f6fbeacbf733e95,0x3f7fbd49bf800000,0x3f7cbe16bf7e3dc9,0x3f4abf18bf513f0e,0x3f39bf2cbf423f22,0x3f65bedbbf6a3ec4,0x3f58bf04bf5f3ef1,
0xbe89bf783e603f7b,0xbeb8bf713ea13f75,0xbd97bf803cc93f80,0xbe2fbf7d3dfb3f7f,0xbf1dbf4e3f133f55,0xbf31bf3e3f273f46,0xbee6bf673ecf3f6d,0xbf09bf5c3efc3f62,
0x3f4e3f22bf3ebf35,0x3f673ef1bf5cbf0e,0x3f783e95bf71bec4,0x3f803dc9bf7dbe48,0x3e163f7fbd49bf80,0x3eac3f75be79bf7b,0x3f043f62bedbbf6d,0x3f2c3f46bf18bf55,
0x3f18bf46bf2c3f35,0x3edbbf62bf043f55,0x3e79bf75beac3f6d,0x3d49bf7fbe163f7b,0x3f7dbdc9bf808000,0x3f71be95bf783e48,0x3f5cbef1bf673ec4,0x3f3ebf22bf4e3f0e,
0x3ecf3f71be89bf7b,0x3f273f4ebf09bf62,0xbe2f3f783ea1bf6d,0x3dfb3f803cc9bf7f,0xbf313f2c3f4abf0e,0xbee63f5c3f13bf46,0xbf7a3e163f7f0000,0xbf5f3edb3f6fbe95,
0x3f6abeacbf773e48,0x3f42bf18bf583ef1,0x3f7c3e79bf73bec4,0x3f7ebd49bf80bdc9,0x3f393f3ebf1dbf55,0x3f653f04bf51bf22,0x3e603f7dbd97bf80,0x3efc3f67beb8bf75,
0xbe95bf7b3dc93f80,0xbf22bf553ef13f6d,0xbf62bf0e3f463f35,0xbf7fbe483f753ec4,0xbf753e483f7f0000,0xbf463f0e3f62bec4,0xbef13f553f22bf35,0xbdc93f7b3e95bf6d,
0xbf753e483f7f8000,0xbf463f0e3f62bec4,0xbef13f553f22bf35,0xbdc93f7b3e95bf6d,0x3e953f7bbdc9bf80,0x3f223f55bef1bf6d,0x3f623f0ebf46bf35,0x3f7f3e48bf75bec4,
0x3e60bf71bee63f55,0xbe89bf7d3cc93f7f,0x3f6fbe79bf7e0000,0x3f27bf2cbf513ef1,0xbf7c3d493f7f3e48,0xbf4a3f043f6abe95,0xbf31bf4e3efc3f6d,0xbf73bedb3f583f22,
0xbf7abeac3f653f0e,0xbf773e163f803dc9,0xbeb8bf783dfb3f80,0xbf42bf3e3f133f62,0x3e2f3f803d97bf7b,0x3f1d3f5cbecfbf75,0xbf393f183f5fbec4,0xbea13f673f09bf46,
0x3eacbf62bf183f35,0xbe79bf7fbd493f7b,0xbf3ebf463f043f6d,0xbf7dbe953f673f0e,0x3edb3f75be16bf80,0x3f5c3f22bf2cbf55,0x3f803dc9bf78bec4,0x3f4ebef1bf713e48,
0xbf71bef13f4e3f35,0xbf783dc93f803e48,0xbf2c3f223f5cbec4,0xbe163f753edbbf55,0x3f67be95bf7d8000,0x3f04bf46bf3e3f0e,0xbd49bf7fbe793f6d,0xbf18bf623eac3f7b,
0x3d97bf78becf3f55,0xbf13bf673e893f7f,0x3f7e3d49bf7abec4,0x3f31bf18bf653e95,0x3ea13f7d3cc9bf7b,0x3f583f2cbf1dbf62,0xbf5f3eac3f7c0000,0xbeb83f5c3f27bf22,
0xbf7fbe793f6a3f0e,0xbf513edb3f77bdc9,0xbdfbbf80be603f6d,0xbf39bf4e3ee63f75,0x3f73be16bf80be48,0x3f09bf3ebf4a3ef1,0x3efc3f71be2fbf80,0x3f6f3f04bf42bf46,
0xbf0ebf6d3e483f80,0xbf7bbec43f553f35,0xbf553ec43f7b0000,0xbe483f6d3f0ebf35,0x3f0e3f6dbe48bf80,0x3f7b3ec4bf55bf35,0x3f55bec4bf7b0000,0x3e48bf6dbf0e3f35,
0xbf553ec43f7b8000,0xbe483f6d3f0ebf35,0x3f0e3f6dbe48bf80,0x3f7b3ec4bf55bf35,0x3f55bec4bf7b8000,0x3e48bf6dbf0e3f35,0xbf0ebf6d3e483f80,0xbf7bbec43f553f35,
0xbf42bf4e3ecf3f7b,0xbf7cbd493f773ef1,0x3f4abedbbf7a0000,0x3cc9bf78bee63f46,0x3f733f04bf39bf55,0x3f58beacbf7ebdc9,0xbefc3f3e3f51bec4,0x3eb83f7d3d97bf75,
0xbf273f183f6abe48,0x3e2f3f803e89bf62,0xbf1dbf673e603f80,0xbf80be793f653f22,0x3ea1bf5cbf313f0e,0xbf09bf713dfb3f7f,0x3f5f3f2cbf13bf6d,0x3f6fbe16bf7fbe95,
0xbf80be953f5c3f35,0xbf183f223f67be48,0x3eac3f7f3e16bf6d,0x3f783ef1bf3ebf55,0x3f2c3f62be79bf80,0x3f7d3dc9bf71bf0e,0x3edbbf46bf4e3ec4,0xbf04bf753d493f7b,
0xbd493f753f04bf35,0x3f4e3f46bedbbf7b,0x3f71bdc9bf7dbec4,0x3e79bf62bf2c3f0e,0x3f3ebef1bf788000,0xbe16bf7fbeac3f55,0xbf67bf223f183f6d,0xbf5c3e953f803e48,
0xbf093f2c3f65be48,0x3efc3f783cc9bf75,0xbecfbf7dbdfb3f6d,0xbf7fbeac3f513f46,0x3f7c3edbbf42bf55,0x3f1dbf18bf6f3dc9,0xbf313f043f770000,0x3ea13f803e60bf62,
0x3f583f3ebee6bf7b,0x3f5fbe79bf80be95,0xbf6a3e163f7e3ec4,0xbd973f713f13bf22,0x3e2fbf67bf273f0e,0xbf4abf4e3eb83f7f,0x3f393f5cbe89bf80,0x3f73bd49bf7abef1,
0xbf46bf553e953f80,0xbf623e483f7f3ec4,0x3dc93f7b3ef1bf35,0x3f753f0ebf22bf6d,0x3f22bf0ebf750000,0xbef1bf7bbdc93f6d,0xbf7fbe483f623f35,0xbe953f553f46bec4,
0xbf223f0e3f758000,0x3ef13f7b3dc9bf6d,0x3f7f3e48bf62bf35,0x3e95bf55bf463ec4,0xbf46bf553e953f80,0xbf623e483f7f3ec4,0x3dc93f7b3ef1bf35,0x3f753f0ebf22bf6d,
0xbf6f3d493f773f0e,0x3d973f783f09bf22,0x3f13bf18bf730000,0xbf1dbf713cc93f75,0xbf31bf673dfb3f7b,0xbf653e163f7c3ef1,0x3f7a3f04bf27bf6d,0x3efcbf2cbf6a3dc9,
0x3eb83f803e89bf55,0x3f7f3e79bf58bf46,0xbf51bf4e3ea13f80,0xbf4a3eac3f803e95,0xbf393edb3f7e3e48,0x3ee63f7d3e2fbf62,0x3e60bf5cbf423ec4,0xbf5fbf3e3ecf3f7f,
0x3e793f7f3edbbf35,0x3f803e95bf4ebf55,0x3e16bf62bf3e3ec4,0xbf71bf223f043f7b,0x3f5c3f46beacbf80,0x3f2cbef1bf7dbe48,0xbf18bf75bd493f6d,0xbf673dc93f783f0e,
0x3f783dc9bf67bf35,0xbd49bf75bf183f0e,0xbf7dbef13f2c3f6d,0xbeac3f463f5cbe48,0x3f04bf22bf718000,0xbf3ebf623e163f7b,0xbf4e3e953f803ec4,0x3edb3f7f3e79bf55,
0x3f5fbe16bf7abf0e,0xbecfbf80bea13f46,0xbf423eac3f803ec4,0x3f133f783dfbbf62,0x3f1dbf04bf7cbe48,0xbf39bf673d973f75,0xbee63f2c3f6f0000,0x3f583f4ebe89bf7f,
0xbefcbf7dbe603f55,0xbf6a3d493f733f22,0x3f273f713cc9bf6d,0x3f51be79bf7ebef1,0xbf4abf5c3e2f3f7b,0xbf313edb3f7f3e95,0x3f653f3ebeb8bf80,0x3f09bf18bf77bdc9,
0xbf6dbf353ec43f80,0xbec43f353f6d0000,0x3f6d3f35bec4bf80,0x3ec4bf35bf6d0000,0xbf6dbf353ec43f80,0xbec43f353f6d0000,0x3f6d3f35bec4bf80,0x3ec4bf35bf6d0000,
0xbec43f353f6d8000,0x3f6d3f35bec4bf80,0x3ec4bf35bf6d8000,0xbf6dbf353ec43f80,0xbec43f353f6d8000,0x3f6d3f35bec4bf80,0x3ec4bf35bf6d8000,0xbf6dbf353ec43f80,
0xbdfb3f5c3f51be48,0x3f803edbbf27bf75,0x3ea1bf3ebf6a0000,0xbf7abf183efc3f7f,0x3e893f7d3f09bf0e,0x3f6f3d49bf65bf46,0xbd97bf71bf313ec4,0xbf7cbe793f4a3f62,
0x3f7e3f04bf13bf7b,0x3cc9bf67bf423e95,0xbf73bf2c3ecf3f80,0xbe603f4e3f5fbdc9,0x3f773e16bf58bf55,0xbeb8bf80bee63f22,0xbf7fbeac3f393f6d,0x3e2f3f783f1dbef1,
0x3f5cbdc9bf71bf35,0xbf2cbf75be163f55,0xbf183ef13f803ec4,0x3f673f46be79bf7b,0x3f783f22bedbbf80,0x3d49bf62bf4e3e48,0xbf7dbe953f3e3f6d,0x3eac3f7f3f04bf0e,
0xbf04bf7fbeac3f35,0xbf3e3e953f7d3f0e,0x3f4e3f62bd49bf6d,0x3edbbf22bf78be48,0x3e79bf46bf678000,0xbf80bef13f183f7b,0x3e163f753f2cbec4,0x3f713dc9bf5cbf55,
0xbf80bedb3f1d3f7b,0x3ea13f7d3f13bef1,0x3f583f5cbd97bf6d,0x3e89bf3ebf6fbdc9,0xbecfbf80befc3f0e,0xbf423e793f7a3f22,0xbe2f3f4e3f650000,0x3f7e3eacbf31bf75,
0x3cc93f673f4abe48,0x3f733e16bf51bf62,0x3f09bf04bf7fbec4,0xbf77bf2c3eb83f7f,0xbf6abd493f5f3f55,0x3f273f783e60bf46,0x3f7c3f18bee6bf80,0xbdfbbf71bf393e95,
0xbf7fbf0e3ef13f80,0x3e953f7b3f22bec4,0x3f46be48bf75bf35,0xbf62bf553dc93f6d,0xbdc93f553f620000,0x3f753e48bf46bf6d,0xbf22bf7bbe953f35,0xbef13f0e3f7f3ec4,
0xbdc93f553f628000,0x3f753e48bf46bf6d,0xbf22bf7bbe953f35,0xbef13f0e3f7f3ec4,0x3f7f3f0ebef1bf80,0xbe95bf7bbf223ec4,0xbf463e483f753f35,0x3f623f55bdc9bf6d,
0x3f513f673d97bf55,0x3dfbbf4ebf6abdc9,0x3cc9bf5cbf5f0000,0xbf65bd493f583f62,0x3e60bf3ebf73be48,0xbf77be793f393f75,0xbf6fbe163f4a3f6d,0x3f423f713e2fbf46,
0x3f13bedbbf7fbf0e,0xbf7ebf183ecf3f7f,0xbf80bf043efc3f80,0x3ee63f803f09bef1,0xbf7abf2c3ea13f7b,0x3e893f783f31be95,0x3eb83f7d3f1dbec4,0x3f27beacbf7cbf22,
0xbf3ebf75be793f35,0xbe163f463f713e48,0x3f673dc9bf4ebf6d,0xbf5cbf62bd493f55,0x3f803ef1bf04bf80,0xbf18bf7fbedb3f0e,0xbeac3f223f7d3ec4,0x3f783e95bf2cbf7b,
0xbf2c3e953f783f35,0x3f7d3f22beacbf7b,0xbedbbf7fbf183ec4,0xbf043ef13f803f0e,0xbd49bf62bf5c8000,0xbf4e3dc93f673f55,0x3f713f46be16bf6d,0xbe79bf75bf3e3e48,
0x3f653f5c3cc9bf55,0xbe60bf71bf4a3dc9,0x3e89bf2cbf7cbec4,0xbf6abe163f423f75,0xbf7fbf183eb83f7b,0x3f133f803efcbef1,0x3dfb3f673f580000,0x3f31be79bf73bf46,
0x3ee6bf04bf80bf0e,0xbf7abeac3f1d3f7f,0xbf77bf3e3e2f3f6d,0x3ecf3f7d3f27be95,0xbd973f4e3f6f3e48,0x3f51bd49bf5fbf62,0x3f7e3edbbf09bf80,0xbf39bf78bea13f22,
0xbf7bbec43f0e3f80,0x3f553f6d3e48bf35,0xbe48bf6dbf550000,0xbf0e3ec43f7b3f35,0x3f7b3ec4bf0ebf80,0xbf55bf6dbe483f35,0x3e483f6d3f550000,0x3f0ebec4bf7bbf35,
0x3e483f6d3f558000,0x3f0ebec4bf7bbf35,0xbf7bbec43f0e3f80,0x3f553f6d3e48bf35,0xbe48bf6dbf558000,0xbf0e3ec43f7b3f35,0x3f7b3ec4bf0ebf80,0xbf55bf6dbe483f35,
0x3f653e16bf39bf7b,0xbf7abf3e3dfb3f62,0xbe89bf71bf510000,0xbecf3f043f7f3f22,0xbf273e793f6f3f55,0x3f7c3edbbefcbf7f,0x3f1d3f803f09bec4,0x3cc9bf4ebf73be95,
0xbee6bf7dbf313e48,0xbe603f2c3f7e3ef1,0xbf77beac3f133f80,0x3f6a3f5c3d97bf46,0x3f423f783eb8bf0e,0xbe2fbf67bf5fbdc9,0x3f4abd49bf58bf6d,0xbf80bf183ea13f75,
0xbedb3ef13f7d3f35,0x3f5c3dc9bf3ebf7b,0xbf80bf223e793f6d,0x3f4e3f753eacbf0e,0x3f713e95bf18bf80,0xbf78bf463d493f55,0x3f2c3f7f3f04bec4,0xbe16bf62bf67be48,
0x3f673f623e16bf35,0xbf04bf7fbf2c3e48,0xbd493f463f783ec4,0x3f18be95bf71bf55,0xbeacbf75bf4e8000,0xbe793f223f803f0e,0x3f3ebdc9bf5cbf6d,0xbf7dbef13edb3f7b,
0xbf13bf80bf273e48,0x3dfb3f5c3f6f3e95,0xbf80bf183e893f6d,0x3f653f673e60bf22,0xbf093eac3f733f55,0x3f5f3e16bf31bf7f,0x3ecf3f783f4a0000,0x3d97bf3ebf7cbef1,
0xbf51bd493f423f7b,0x3f7e3f04beb8bf75,0x3cc93f4e3f773ec4,0x3ee6bedbbf7abf46,0x3f583f713ea1bf0e,0xbefcbf7dbf393dc9,0x3f6a3e79bf1dbf80,0xbf7fbf2c3e2f3f62,
0xbf62be483f223f80,0x3f7f3f0ebe95bf6d,0xbf75bf55bdc93f35,0x3f463f7b3ef1bec4,0xbef1bf7bbf460000,0x3dc93f553f753ec4,0x3e95bf0ebf7fbf35,0xbf223e483f623f6d,
0x3ef13f7b3f468000,0xbdc9bf55bf75bec4,0xbe953f0e3f7f3f35,0x3f22be48bf62bf6d,0xbf62be483f223f80,0x3f7f3f0ebe95bf6d,0xbf75bf55bdc93f35,0x3f463f7b3ef1bec4,
0x3cc9bf3ebf7ebf0e,0xbea13f043f7c3f46,0xbf09bf7dbf420000,0x3e893f673f6a3e95,0x3f6f3eacbefcbf7b,0xbf7fbf183e603f62,0x3f13be79bf65bf6d,0xbf4abd493f393f7f,
0xbf80bf2c3dfb3f55,0x3f733f5c3e2fbf22,0xbf58be163f273f80,0x3f773edbbecfbf75,0xbeb8bf71bf5fbe48,0x3d973f4e3f7a3ef1,0xbf51bf78bee63ec4,0x3f1d3f803f31bdc9,
0x3f7d3f463d49bf35,0xbf71bf62be793f0e,0x3f5c3f753edbbec4,0xbf3ebf7fbf183e48,0x3f4e3dc9bf2cbf80,0xbf67be953f043f7b,0x3f783ef1beacbf6d,0xbf80bf223e163f55,
0x3e16bf22bf80bf35,0xbeac3ef13f783f55,0x3f04be95bf67bf6d,0xbf2c3dc93f4e3f7b,0xbf18bf7fbf3e8000,0x3edb3f753f5c3e48,0xbe79bf62bf71bec4,0x3d493f463f7d3f0e,
0x3dfb3f4e3f7c3f0e,0xbcc9bf3ebf7fbf22,0x3ea13f673f6f3ec4,0xbe60bf5cbf77bef1,0x3efc3f783f583e48,0xbecfbf71bf65be95,0x3f273f803f390000,0xbf13bf7dbf4abdc9,
0x3f7e3f18be2fbf55,0xbf80bf2c3d973f46,0x3f733edbbeb8bf6d,0xbf7abf043e893f62,0x3f5f3e79bf09bf7b,0xbf6abeac3ee63f75,0x3f423d49bf31bf80,0xbf51be163f1d3f7f,
0x3f350000bf353f80,0xbf3500003f35bf80,0x3f350000bf353f80,0xbf3500003f35bf80,0x3f350000bf353f80,0xbf3500003f35bf80,0x3f350000bf353f80,0xbf3500003f35bf80,
0xbf353f80bf358000,0x3f35bf803f358000,0xbf353f80bf358000,0x3f35bf803f358000,0xbf353f80bf358000,0x3f35bf803f358000,0xbf353f80bf358000,0x3f35bf803f358000,
0x3efcbf5cbf093f55,0x3ecfbf67bee63f62,0x3f27bf3ebf313f35,0x3f13bf4ebf1d3f46,0x3dfbbf7dbe2f3f7b,0x3cc9bf80bd973f7f,0x3ea1bf71beb83f6d,0x3e60bf78be893f75,
0xbf5fbf043f583f0e,0xbf6abedb3f653ef1,0xbf42bf2c3f393f35,0xbf51bf183f4a3f22,0xbf7ebe163f7c3e48,0xbf80bd493f7f3dc9,0xbf73beac3f6f3ec4,0xbf7abe793f773e95,
0x3f18bf46bf2c3f35,0x3edbbf62bf043f55,0x3e79bf75beac3f6d,0x3d49bf7fbe163f7b,0x3f7dbdc9bf800000,0x3f71be95bf783e48,0x3f5cbef1bf673ec4,0x3f3ebf22bf4e3f0e,
0xbf4ebf223f3e3f35,0xbf67bef13f5c3f0e,0xbf78be953f713ec4,0xbf80bdc93f7d3e48,0xbe16bf7f3d493f80,0xbeacbf753e793f7b,0xbf04bf623edb3f6d,0xbf2cbf463f183f55,
0x3eb8bf67befc3f55,0x3d97bf7dbe603f75,0x3f51bf04bf653ec4,0x3f1dbf3ebf393f22,0x3f803d49bf7ebe48,0x3f73be79bf7c3dc9,0x3f583f18bf42bf35,0x3f773eacbf6abef1,
0xbf6fbedb3f5f3f0e,0xbf7fbe163f7a3e95,0xbf13bf5c3ee63f6d,0xbf4abf2c3f313f46,0xbcc9bf80bdfb3f7b,0xbea1bf783e2f3f7f,0x3f09bf4ebf273f35,0x3e89bf71becf3f62,
0x3e953f7bbdc9bf80,0x3f223f55bef1bf6d,0x3f623f0ebf46bf35,0x3f7f3e48bf75bec4,0x3f75be48bf7f0000,0x3f46bf0ebf623ec4,0x3ef1bf55bf223f35,0x3dc9bf7bbe953f6d,
0x3f75be48bf7f8000,0x3f46bf0ebf623ec4,0x3ef1bf55bf223f35,0x3dc9bf7bbe953f6d,0xbe95bf7b3dc93f80,0xbf22bf553ef13f6d,0xbf62bf0e3f463f35,0xbf7fbe483f753ec4,
0x3f093f67bea1bf7b,0x3f5f3f18bf39bf46,0xbecf3f5c3f1dbf35,0x3d973f803e2fbf75,0x3f13bf3ebf423f0e,0x3dfbbf78beb83f62,0x3f803e16bf77bec4,0x3f65beacbf7a3dc9,
0x3f58bedbbf733e48,0x3efcbf4ebf313f22,0x3f6a3f04bf4abf35,0x3f7f3d49bf7cbe95,0xbf51bf2c3f273f55,0xbf7ebe793f6f3ef1,0x3cc9bf7dbe893f6d,0xbee6bf713e603f7f,
0x3f713ef1bf4ebf35,0x3f78bdc9bf80be48,0x3f2cbf22bf5c3ec4,0x3e16bf75bedb3f55,0xbf673e953f7d0000,0xbf043f463f3ebf0e,0x3d493f7f3e79bf6d,0x3f183f62beacbf7b,
0x3eacbf62bf183f35,0xbe79bf7fbd493f7b,0xbf3ebf463f043f6d,0xbf7dbe953f673f0e,0x3edb3f75be16bf80,0x3f5c3f22bf2cbf55,0x3f803dc9bf78bec4,0x3f4ebef1bf713e48,
0x3f42bf04bf6f3e48,0x3e2fbf71befc3f46,0x3f4a3f3ebf09bf6d,0x3f803e16bf73bef1,0xbee63f4e3f39bf0e,0x3e603f803dfbbf75,0xbf77bedb3f513f35,0xbf6a3e793f7f3dc9,
0xbf27bf5c3eb83f7b,0xbf7cbeac3f5f3f22,0x3f1dbf2cbf583ec4,0xbcc9bf7dbea13f62,0x3f653f18bf31bf55,0x3f7abd49bf7ebe95,0xbe893f673f13bf35,0x3ecf3f78bd97bf7f,
0xbf0ebf6d3e483f80,0xbf7bbec43f553f35,0xbf553ec43f7b0000,0xbe483f6d3f0ebf35,0x3f0e3f6dbe48bf80,0x3f7b3ec4bf55bf35,0x3f55bec4bf7b0000,0x3e48bf6dbf0e3f35,
0xbf553ec43f7b8000,0xbe483f6d3f0ebf35,0x3f0e3f6dbe48bf80,0x3f7b3ec4bf55bf35,0x3f55bec4bf7b8000,0x3e48bf6dbf0e3f35,0xbf0ebf6d3e483f80,0xbf7bbec43f553f35,
0xbf7fbe163f6f3f0e,0xbf133f2c3f5fbe95,0x3dfbbf71bf093f35,0xbf31bf5c3ea13f7f,0x3f65be79bf80be48,0x3e60bf67bf1d3f22,0x3e893f803e2fbf6d,0x3f6a3f18bf27bf62,
0x3d973f7d3eb8bf55,0x3f513f3ebefcbf75,0xbf7ebeac3f583f35,0xbf393f043f73bdc9,0xbee6bf783cc93f7b,0xbf7abedb3f4a3f46,0x3f77bd49bf7cbec4,0x3ecfbf4ebf423ef1,
0xbd493f753f04bf35,0x3f4e3f46bedbbf7b,0x3f71bdc9bf7dbec4,0x3e79bf62bf2c3f0e,0x3f3ebef1bf780000,0xbe16bf7fbeac3f55,0xbf67bf223f183f6d,0xbf5c3e953f803e48,
0x3f803e95bf5cbf35,0x3f18bf22bf673e48,0xbeacbf7fbe163f6d,0xbf78bef13f3e3f55,0xbf2cbf623e793f80,0xbf7dbdc93f713f0e,0xbedb3f463f4ebec4,0x3f043f75bd49bf7b,
0x3f7a3d49bf73bf0e,0x3e89bf5cbf393ef1,0xbeb83f4e3f4abec4,0x3f273f67be2fbf7f,0xbf13bf713d973f7b,0xbf7ebe163f6a3f22,0x3f803e79bf5fbf35,0x3ee6bf3ebf583e95,
0xbe60bf80bea13f55,0xbf77bf043f313f62,0x3f6f3f18bf1dbf6d,0x3f42bedbbf7cbdc9,0xbf513eac3f7f3e48,0x3dfb3f7d3ecfbf46,0xbcc9bf78befc3f35,0xbf65bf2c3f093f75,
0x3f463f55be95bf80,0x3f62be48bf7fbec4,0xbdc9bf7bbef13f35,0xbf75bf0e3f223f6d,0xbf223f0e3f750000,0x3ef13f7b3dc9bf6d,0x3f7f3e48bf62bf35,0x3e95bf55bf463ec4,
0x3f22bf0ebf758000,0xbef1bf7bbdc93f6d,0xbf7fbe483f623f35,0xbe953f553f46bec4,0x3f463f55be95bf80,0x3f62be48bf7fbec4,0xbdc9bf7bbef13f35,0xbf75bf0e3f223f6d,
0x3ecfbf3ebf5f3e48,0xbf42bf5c3e603f7f,0x3e2f3f7d3ee6bf35,0x3f7e3edbbf39bf62,0x3f803eacbf4abf55,0x3ea1bf4ebf513e95,0xbf583e793f7f3ec4,0x3e893f803eb8bf46,
0xbf6abf2c3efc3f7b,0xbf273f043f7a3dc9,0x3f7c3e16bf65bf35,0x3dfbbf67bf313ef1,0x3cc9bf71bf1d3f0e,0xbf73bf183f133f75,0x3f093f783d97bf6d,0x3f773d49bf6fbf22,
0xbf78bdc93f673f35,0x3d493f753f18bf0e,0x3f7d3ef1bf2cbf6d,0x3eacbf46bf5c3e48,0xbf043f223f710000,0x3f3e3f62be16bf7b,0x3f4ebe95bf80bec4,0xbedbbf7fbe793f55,
0x3e793f7f3edbbf35,0x3f803e95bf4ebf55,0x3e16bf62bf3e3ec4,0xbf71bf223f043f7b,0x3f5c3f46beacbf80,0x3f2cbef1bf7dbe48,0xbf18bf75bd493f6d,0xbf673dc93f783f0e,
0x3f773f18bf09bf7b,0x3eb8bf3ebf653dc9,0xbf7fbedb3f313f6d,0xbe2f3f5c3f4abe95,0x3f7e3e79bf51bf55,0xbcc9bf71bf273ef1,0xbf73bd493f6a3f35,0x3e603f7d3efcbf22,
0x3e89bf4ebf583e48,0xbf6fbf2c3ee63f7f,0xbd973f673f39bec4,0x3f7c3f04bf1dbf75,0xbdfbbf78bf133f0e,0xbf80beac3f423f62,0x3ea13f803ecfbf35,0x3f7a3e16bf5fbf46,
0xbf6dbf353ec43f80,0xbec43f353f6d0000,0x3f6d3f35bec4bf80,0x3ec4bf35bf6d0000,0xbf6dbf353ec43f80,0xbec43f353f6d0000,0x3f6d3f35bec4bf80,0x3ec4bf35bf6d0000,
0xbec43f353f6d8000,0x3f6d3f35bec4bf80,0x3ec4bf35bf6d8000,0xbf6dbf353ec43f80,0xbec43f353f6d8000,0x3f6d3f35bec4bf80,0x3ec4bf35bf6d8000,0xbf6dbf353ec43f80,
0x3f1d3f783e2fbf55,0x3f39beacbf7fbef1,0xbee6bf80beb83f35,0xbf583e163f773f22,0x3f5f3f4ebe60bf7b,0x3ecfbf2cbf73bdc9,0xbf42bf673cc93f6d,0xbf133f043f7e3e95,
0x3f4abe79bf7cbf0e,0xbf31bf71bd973f62,0xbf653d493f6f3f35,0x3f093f7d3e89bf46,0x3efcbf18bf7abe48,0xbf6abf3e3ea13f7f,0xbf273edb3f803ec4,0x3f513f5cbdfbbf75,
0xbf04bf7fbeac3f35,0xbf3e3e953f7d3f0e,0x3f4e3f62bd49bf6d,0x3edbbf22bf78be48,0x3e79bf46bf670000,0xbf80bef13f183f7b,0x3e163f753f2cbec4,0x3f713dc9bf5cbf55,
0xbf5c3dc93f713f35,0x3f2c3f753e16bf55,0x3f18bef1bf80bec4,0xbf67bf463e793f7b,0xbf78bf223edb3f80,0xbd493f623f4ebe48,0x3f7d3e95bf3ebf6d,0xbeacbf7fbf043f0e,
0x3f393f713dfbbf55,0x3ee6bf18bf7cbe95,0xbe60bf78bf273ec4,0xbf5f3d493f6a3f46,0xbeb83f2c3f773e48,0x3f7f3f04bf09bf7f,0x3f51be16bf73bf35,0xbf4abf67bcc93f62,
0x3f31beacbf7ebf0e,0xbf65bf4e3e2f3f75,0xbf7abe793f423f6d,0x3efc3f803ecfbf22,0x3f6f3f3ebe89bf7b,0x3d97bf5cbf583dc9,0xbf13bf7dbea13f35,0xbf1d3edb3f803ef1,
0x3f7f3f0ebef1bf80,0xbe95bf7bbf223ec4,0xbf463e483f753f35,0x3f623f55bdc9bf6d,0x3dc9bf55bf620000,0xbf75be483f463f6d,0x3f223f7b3e95bf35,0x3ef1bf0ebf7fbec4,
0x3dc9bf55bf628000,0xbf75be483f463f6d,0x3f223f7b3e95bf35,0x3ef1bf0ebf7fbec4,0xbf7fbf0e3ef13f80,0x3e953f7b3f22bec4,0x3f46be48bf75bf35,0xbf62bf553dc93f6d,
0xbf7cbeac3f273f7b,0x3f1d3f7d3eb8bf22,0x3f313f783e89bf35,0x3ea1bf2cbf7abe95,0x3f093f803ee6bf0e,0x3efcbf04bf80bef1,0x3ecfbf18bf7ebec4,0xbf7fbedb3f133f7f,
0x3e2f3f713f42be48,0x3f4abe16bf6fbf46,0x3f39be79bf77bf35,0xbf73bf3e3e603f75,0x3f58bd49bf65bf55,0xbf5fbf5c3cc93f62,0xbf6abf4e3dfb3f6d,0x3d973f673f51bdc9,
0x3f2cbe95bf78bf35,0xbf7dbf223eac3f7b,0x3edb3f7f3f18bec4,0x3f04bef1bf80bf0e,0x3d493f623f5c0000,0x3f4ebdc9bf67bf55,0xbf71bf463e163f6d,0x3e793f753f3ebe48,
0xbf3ebf75be793f35,0xbe163f463f713e48,0x3f673dc9bf4ebf6d,0xbf5cbf62bd493f55,0x3f803ef1bf04bf80,0xbf18bf7fbedb3f0e,0xbeac3f223f7d3ec4,0x3f783e95bf2cbf7b,
0x3ea13f783f39be48,0x3f09bedbbf7ebf22,0x3f5f3d49bf51bf6d,0xbf6fbf4e3d973f62,0xbf27bf7dbecf3f0e,0xbe2f3f3e3f773e95,0xbf1d3eac3f7a3f35,0x3f803f04bee6bf7f,
0x3f733e79bf31bf7b,0xbf58bf67bdfb3f46,0xbefcbf80bf133ec4,0xbeb83f183f7f3ef1,0xbf423e163f6a3f55,0x3f7c3f2cbe89bf75,0x3f4a3f713e60bf35,0xbcc9bf5cbf65bdc9,
0xbf7bbec43f0e3f80,0x3f553f6d3e48bf35,0xbe48bf6dbf550000,0xbf0e3ec43f7b3f35,0x3f7b3ec4bf0ebf80,0xbf55bf6dbe483f35,0x3e483f6d3f550000,0x3f0ebec4bf7bbf35,
0x3e483f6d3f558000,0x3f0ebec4bf7bbf35,0xbf7bbec43f0e3f80,0x3f553f6d3e48bf35,0xbe48bf6dbf558000,0xbf0e3ec43f7b3f35,0x3f7b3ec4bf0ebf80,0xbf55bf6dbe483f35,
0x3ea1bf18bf80bf0e,0xbf58bd493f4a3f75,0xbf5fbf67be2f3f35,0x3eb83f783f42bdc9,0x3d973f5c3f6a3e48,0x3f13beacbf77bf46,0x3f7e3f2cbe60bf6d,0xbf31bf7dbee63ef1,
0xbf73bf4e3cc93f55,0x3f093f803f1dbe95,0xbefc3edb3f7c3f35,0x3f6f3e79bf27bf7f,0x3f7f3f04becfbf7b,0xbf51bf71be893f22,0x3dfbbf3ebf7abec4,0xbf393e163f653f62,
0x3f673f623e16bf35,0xbf04bf7fbf2c3e48,0xbd493f463f783ec4,0x3f18be95bf71bf55,0xbeacbf75bf4e0000,0xbe793f223f803f0e,0x3f3ebdc9bf5cbf6d,0xbf7dbef13edb3f7b,
0x3edbbef1bf7dbf35,0xbf5cbdc93f3e3f7b,0x3f803f22be79bf6d,0xbf4ebf75beac3f0e,0xbf71be953f183f80,0x3f783f46bd49bf55,0xbf2cbf7fbf043ec4,0x3e163f623f673e48,
0xbe2f3f2c3f7f3f0e,0x3f1dbe79bf6abf62,0x3f393f7d3efcbec4,0xbea1bf71bf58bdc9,0x3f7a3edbbee6bf7b,0xbf77bf4ebcc93f46,0x3eb8bf04bf7ebf35,0xbf423d493f513f75,
0x3f7c3f3ebd97bf55,0xbf4abf78becf3ef1,0x3f31be16bf5fbf6d,0xbf73beac3f093f7f,0xbe60bf67bf65be48,0xbe893f183f803f22,0xbf6fbf5cbdfb3f35,0x3f273f803f13be95,
0x3f623e48bf22bf80,0xbf7fbf0e3e953f6d,0x3f753f553dc9bf35,0xbf46bf7bbef13ec4,0x3ef13f7b3f460000,0xbdc9bf55bf75bec4,0xbe953f0e3f7f3f35,0x3f22be48bf62bf6d,
0xbef1bf7bbf468000,0x3dc93f553f753ec4,0x3e95bf0ebf7fbf35,0xbf223e483f623f6d,0x3f623e48bf22bf80,0xbf7fbf0e3e953f6d,0x3f753f553dc9bf35,0xbf46bf7bbef13ec4,
0x3f313f803f1dbe48,0xbee6bf78bf51bdc9,0x3f7a3f4e3d97bf35,0xbf5fbf71beb83ef1,0xbecf3edb3f773f55,0x3f27be16bf58bf75,0x3e2f3f5c3f733ec4,0x3dfbbf2cbf80bf22,
0x3f39bd49bf4abf7b,0xbf65be793f133f7f,0x3e60bf18bf7fbf35,0xbefc3eac3f6f3f62,0x3f6a3f673e89bf0e,0xbf42bf7dbf093e95,0x3f7c3f04bea1bf6d,0xbf7ebf3e3cc93f46,
0xbe163f223f803f35,0x3eacbef1bf78bf55,0xbf043e953f673f6d,0x3f2cbdc9bf4ebf7b,0x3f183f7f3f3e0000,0xbedbbf75bf5cbe48,0x3e793f623f713ec4,0xbd49bf46bf7dbf0e,
0x3f7d3f463d49bf35,0xbf71bf62be793f0e,0x3f5c3f753edbbec4,0xbf3ebf7fbf183e48,0x3f4e3dc9bf2cbf80,0xbf67be953f043f7b,0x3f783ef1beacbf6d,0xbf80bf223e163f55,
0xbf1d3e163f513f7b,0x3f31bd49bf42bf7f,0xbee63eac3f6a3f6d,0x3f09be79bf5fbf75,0xbe893f043f7a3f55,0x3eb8bedbbf73bf62,0xbd973f2c3f803f35,0x3e2fbf18bf7ebf46,
0x3f4a3f7d3f13be48,0xbf39bf80bf273dc9,0x3f653f713ecfbec4,0xbf58bf78befc3e95,0x3f773f5c3e60bf0e,0xbf6fbf67bea13ef1,0x3f7f3f3e3cc9bf35,0xbf7cbf4ebdfb3f22,
};
__device__ __align__(1024) uint8_t g_hT[32 * 262144];
__device__ __align__(1024) bf16 g_U[128 * 2 * 8 * 1024];
__device__ __align__(128) float g_gp[128 * 256];
__device__ __align__(128) uint4 g_agg[16 * 512];
#define CS 32
__device__ __align__(128) unsigned g_cnt[8 * 32];
constexpr int CNT_U = 0, CNT_V = 1, CNT_H = 2  , CNT_DONE = 4, CNT_EPOCH = 5;
#define PROFK(i) do { } while (0)
#define PROFC(i) do { } while (0)
#define PROF(i) do { } while (0)
#define PROFX(i) do { } while (0)
#define PROFS(i) do { } while (0)
#define PROFG(i) do { } while (0)

constexpr int SLOT = 32768;
constexpr int OFF_HS = 4 * SLOT;
constexpr int OFF_W = OFF_HS + 16384;
constexpr int OFF_F = OFF_W + 2 * 18432;
constexpr int OFF_G = OFF_F + 8192;
constexpr int OFF_K = OFF_G + 1024;
constexpr int OFF_GW = OFF_K + 2048;
constexpr int OFF_U = 6 * SLOT;
constexpr int OFF_BAR = OFF_U + 32768;
constexpr int OFF_SC = OFF_BAR + 320;
constexpr int OFF_KEPT = OFF_SC + 512;
constexpr int OFF_PROF = OFF_KEPT + 64;
constexpr int SMEM_BYTES = OFF_PROF;
constexpr int BAR_FULL = 0  , BAR_X = 10, BAR_U = 11, BAR_W = 12, BAR_T = 13, BAR_F = 14  ,
              BAR_EMPTY = 17  , BAR_HW = 22  , BAR_WR = 25, BAR_VW = 26, BAR_S1 = 27,
              BAR_XC = 28  , BAR_HR = 32,
              BAR_CD = 33, BAR_C = 34  , BAR_HD = 36  ;

#define DEVI __device__ __forceinline__
constexpr unsigned SPIN_LIMIT = 1u << 22;

DEVI uint32_t smem_u32(const void* p) { return (uint32_t)__cvta_generic_to_shared(p); }
DEVI uint64_t gtime() { uint64_t t; asm volatile("mov.u64 %0, %%globaltimer;" : "=l"(t)); return t; }
DEVI void mbar_init(uint32_t bar, uint32_t cnt) { asm volatile("mbarrier.init.shared::cta.b64 [%0], %1;" :: "r"(bar), "r"(cnt) : "memory"); }
DEVI void mbar_expect_tx(uint32_t bar, uint32_t bytes) { asm volatile("mbarrier.arrive.expect_tx.shared::cta.b64 _, [%0], %1;" :: "r"(bar), "r"(bytes) : "memory"); }
DEVI void mbar_arrive(uint32_t bar) { asm volatile("mbarrier.arrive.shared::cta.b64 _, [%0];" :: "r"(bar) : "memory"); }
DEVI void mbar_wait(uint32_t bar, uint32_t parity) {
    asm volatile("{\n.reg .pred p;\n.reg .u32 n;\nmov.u32 n, 0;\n"
                 "LW:\nmbarrier.try_wait.parity.shared::cta.b64 p, [%0], %1;\n@p bra LD;\n"
                 "add.u32 n, n, 1;\nsetp.lt.u32 p, n, %2;\n@p bra LW;\nLD:\n}"
                 :: "r"(bar), "r"(parity), "n"(1 << 17) : "memory");
}
DEVI bool elect() {
    uint32_t p;
    asm volatile("{\n.reg .pred P;\nelect.sync _|P, 0xffffffff;\nselp.u32 %0, 1, 0, P;\n}" : "=r"(p));
    return p;
}
DEVI void fence_barrier_init() { asm volatile("fence.mbarrier_init.release.cluster;" ::: "memory"); }
DEVI void fence_proxy_async_smem() { asm volatile("fence.proxy.async.shared::cta;" ::: "memory"); }
DEVI void helper_sync() { asm volatile("bar.sync 1, 128;" ::: "memory"); }

DEVI void pause(unsigned n) {
    asm volatile("{\n.reg .pred p;\n.reg .u32 a, b;\nmov.u32 a, %%clock;\n"
                 "LP:\nmov.u32 b, %%clock;\nsub.u32 b, b, a;\nsetp.lt.u32 p, b, %0;\n@p bra LP;\n}" :: "r"(n) : "memory");
}
DEVI void sched_fence() { asm volatile("{\n.reg .pred p;\n.reg .b32 n;\nLP:\nactivemask.b32 n;\nsetp.eq.u32 p, n, 0;\n@p bra LP;\n}" ::: "memory"); }
#define P_POLL 0
#define NPOLL 1
DEVI void wait_counter(const unsigned* p, unsigned target) {
    unsigned v[NPOLL];
    auto ld = [&](int i) { asm volatile("ld.relaxed.gpu.global.u32 %0, [%1];" : "=r"(v[i]) : "l"(p) : "memory"); };
#pragma unroll
    for (int i = 0; i < NPOLL; i++) { if (i) pause(200); ld(i); }
#pragma unroll 1
    for (unsigned n = 0; n < SPIN_LIMIT; n++) {
#pragma unroll
        for (int i = 0; i < NPOLL; i++) {
            if ((int)(v[i] - target) >= 0) return;
            if (P_POLL) pause(P_POLL);
            ld(i);
        }
    }
}
DEVI void signal_counter(unsigned* p) {
    asm volatile("red.relaxed.gpu.global.add.u32 [%0], 1;" :: "l"(p) : "memory");
}

DEVI void tma_load_3d(uint32_t dst, const CUtensorMap* map, uint32_t bar, int c0, int c1, int c2) {
    asm volatile("cp.async.bulk.tensor.3d.shared::cluster.global.mbarrier::complete_tx::bytes [%0], [%1, {%3, %4, %5}], [%2];"
        :: "r"(dst), "l"(map), "r"(bar), "r"(c0), "r"(c1), "r"(c2) : "memory");
}
DEVI void tma_load_4d(uint32_t dst, const CUtensorMap* map, uint32_t bar, int c0, int c1, int c2, int c3) {
    asm volatile("cp.async.bulk.tensor.4d.shared::cluster.global.mbarrier::complete_tx::bytes [%0], [%1, {%3, %4, %5, %6}], [%2];"
        :: "r"(dst), "l"(map), "r"(bar), "r"(c0), "r"(c1), "r"(c2), "r"(c3) : "memory");
}
DEVI void tma_store_4d(const CUtensorMap* map, uint32_t src, int c0, int c1, int c2, int c3) {
    asm volatile("cp.async.bulk.tensor.4d.global.shared::cta.bulk_group [%0, {%2, %3, %4, %5}], [%1];"
        :: "l"(map), "r"(src), "r"(c0), "r"(c1), "r"(c2), "r"(c3) : "memory");
}
DEVI void bulk_load(uint32_t dst, const void* src, uint32_t bytes, uint32_t bar) {
    asm volatile("cp.async.bulk.shared::cluster.global.mbarrier::complete_tx::bytes [%0], [%1], %2, [%3];"
        :: "r"(dst), "l"(src), "r"(bytes), "r"(bar) : "memory");
}
DEVI void bulk_prefetch_l2(const void* src, uint32_t bytes) {
    asm volatile("cp.async.bulk.prefetch.L2.global [%0], %1;" :: "l"(src), "r"(bytes) : "memory");
}
DEVI void tma_store_3d(const CUtensorMap* map, uint32_t src, int c0, int c1, int c2) {
    asm volatile("cp.async.bulk.tensor.3d.global.shared::cta.bulk_group [%0, {%2, %3, %4}], [%1];"
        :: "l"(map), "r"(src), "r"(c0), "r"(c1), "r"(c2) : "memory");
}
DEVI void bulk_store(void* dst, uint32_t src, uint32_t bytes) {
    asm volatile("cp.async.bulk.global.shared::cta.bulk_group [%0], [%1], %2;" :: "l"(dst), "r"(src), "r"(bytes) : "memory");
}
DEVI void bulk_commit() { asm volatile("cp.async.bulk.commit_group;" ::: "memory"); }
DEVI void bulk_wait0() { asm volatile("cp.async.bulk.wait_group 0;" ::: "memory"); }

DEVI void wgmma_fence() { asm volatile("wgmma.fence.sync.aligned;" ::: "memory"); }
DEVI void wgmma_commit() { asm volatile("wgmma.commit_group.sync.aligned;" ::: "memory"); }
template<int N> DEVI void wgmma_wait() { asm volatile("wgmma.wait_group.sync.aligned %0;" :: "n"(N) : "memory"); }
template<int N> DEVI void wgmma_wait_all(float (&d)[N]) {
    wgmma_wait<0>();
#pragma unroll
    for (int i = 0; i < N; i++) asm volatile("" : "+f"(d[i]) :: "memory");
}
template<int R> DEVI void reg_alloc() { asm volatile("setmaxnreg.inc.sync.aligned.u32 %0;" :: "n"(R)); }
template<int R> DEVI void reg_dealloc() { asm volatile("setmaxnreg.dec.sync.aligned.u32 %0;" :: "n"(R)); }

DEVI uint64_t make_desc(uint32_t addr, uint32_t lbo, uint32_t sbo, uint32_t mode = 1) {
    return (uint64_t)(((addr & 0x3FFFF) >> 4) | ((lbo >> 4) << 16)) | ((uint64_t)((sbo >> 4) | (mode << 30)) << 32);
}

#define ACC8(a, o) "+f"(a[o+0]), "+f"(a[o+1]), "+f"(a[o+2]), "+f"(a[o+3]), "+f"(a[o+4]), "+f"(a[o+5]), "+f"(a[o+6]), "+f"(a[o+7])
#define OUT8(a, o) "=f"(a[o+0]), "=f"(a[o+1]), "=f"(a[o+2]), "=f"(a[o+3]), "=f"(a[o+4]), "=f"(a[o+5]), "=f"(a[o+6]), "=f"(a[o+7])
#define ACC32(a, o) ACC8(a, o), ACC8(a, o+8), ACC8(a, o+16), ACC8(a, o+24)

template<int TA, int TB>
DEVI void wgmma_n128(float (&d)[64], uint64_t da, uint64_t db, int scale_d) {
    asm volatile("{\n.reg .pred p;\nsetp.ne.b32 p, %66, 0;\n"
        "wgmma.mma_async.sync.aligned.m64n128k16.f32.bf16.bf16 "
        "{%0, %1, %2, %3, %4, %5, %6, %7, %8, %9, %10, %11, %12, %13, %14, %15, "
        "%16, %17, %18, %19, %20, %21, %22, %23, %24, %25, %26, %27, %28, %29, %30, %31, "
        "%32, %33, %34, %35, %36, %37, %38, %39, %40, %41, %42, %43, %44, %45, %46, %47, "
        "%48, %49, %50, %51, %52, %53, %54, %55, %56, %57, %58, %59, %60, %61, %62, %63}, "
        "%64, %65, p, 1, 1, %67, %68;\n}\n"
        : ACC32(d, 0), ACC32(d, 32)
        : "l"(da), "l"(db), "r"(scale_d), "n"(TA), "n"(TB));
}
#define SS_N16 "{\n.reg .pred p;\nsetp.ne.b32 p, 0, 0;\n" \
        "wgmma.mma_async.sync.aligned.m64n16k16.f32.bf16.bf16 " \
        "{%0, %1, %2, %3, %4, %5, %6, %7}, %8, %9, p, 1, 1, %10, 0;\n}\n"
template<int TA> DEVI void wgmma_n16(float* d, uint64_t da, uint64_t db) {
    asm volatile(SS_N16 : OUT8(d, 0) : "l"(da), "l"(db), "n"(TA));
}
#define SS_N8 "{\n.reg .pred p;\nsetp.ne.b32 p, %6, 0;\n" \
        "wgmma.mma_async.sync.aligned.m64n8k16.f32.bf16.bf16 {%0, %1, %2, %3}, %4, %5, p, 1, 1, 0, 0;\n}\n"
DEVI void wgmma_n8(float (&d)[4], uint64_t da, uint64_t db, bool add) {
    if (add) asm volatile(SS_N8 : "+f"(d[0]), "+f"(d[1]), "+f"(d[2]), "+f"(d[3]) : "l"(da), "l"(db), "n"(1));
    else asm volatile(SS_N8 : "=f"(d[0]), "=f"(d[1]), "=f"(d[2]), "=f"(d[3]) : "l"(da), "l"(db), "n"(0));
}
#define RS_N64 "{\n.reg .pred p;\nsetp.ne.b32 p, %37, 0;\n" \
        "wgmma.mma_async.sync.aligned.m64n64k16.f32.bf16.bf16 " \
        "{%0, %1, %2, %3, %4, %5, %6, %7, %8, %9, %10, %11, %12, %13, %14, %15, " \
        "%16, %17, %18, %19, %20, %21, %22, %23, %24, %25, %26, %27, %28, %29, %30, %31}, " \
        "{%32, %33, %34, %35}, %36, p, 1, 1, %38;\n}\n"
template<int SCALE_D, int TB = 0>
DEVI void wgmma_rs_n64(float (&d)[32], const uint32_t (&a)[4], uint64_t db) {
    if (SCALE_D) asm volatile(RS_N64 : ACC32(d, 0) : "r"(a[0]), "r"(a[1]), "r"(a[2]), "r"(a[3]), "l"(db), "n"(1), "n"(TB));
    else asm volatile(RS_N64 : OUT8(d, 0), OUT8(d, 8), OUT8(d, 16), OUT8(d, 24) : "r"(a[0]), "r"(a[1]), "r"(a[2]), "r"(a[3]), "l"(db), "n"(0), "n"(TB));
}
#define SS_N64 "{\n.reg .pred p;\nsetp.ne.b32 p, %34, 0;\n" \
        "wgmma.mma_async.sync.aligned.m64n64k16.f32.bf16.bf16 " \
        "{%0, %1, %2, %3, %4, %5, %6, %7, %8, %9, %10, %11, %12, %13, %14, %15, " \
        "%16, %17, %18, %19, %20, %21, %22, %23, %24, %25, %26, %27, %28, %29, %30, %31}, " \
        "%32, %33, p, 1, 1, 0, 1;\n}\n"
template<int SCALE_D> DEVI void wgmma_ss_n64(float (&d)[32], uint64_t da, uint64_t db) {
    if (SCALE_D) asm volatile(SS_N64 : ACC32(d, 0) : "l"(da), "l"(db), "n"(1));
    else asm volatile(SS_N64 : OUT8(d, 0), OUT8(d, 8), OUT8(d, 16), OUT8(d, 24) : "l"(da), "l"(db), "n"(0));
}
DEVI void ldsm_x4_t(uint32_t (&r)[4], uint32_t addr) {
    asm volatile("ldmatrix.sync.aligned.m8n8.x4.trans.shared.b16 {%0, %1, %2, %3}, [%4];"
        : "=r"(r[0]), "=r"(r[1]), "=r"(r[2]), "=r"(r[3]) : "r"(addr) : "memory");
}
DEVI void ldsm_x4(uint32_t (&r)[4], uint32_t addr) {
    asm volatile("ldmatrix.sync.aligned.m8n8.x4.shared.b16 {%0, %1, %2, %3}, [%4];"
        : "=r"(r[0]), "=r"(r[1]), "=r"(r[2]), "=r"(r[3]) : "r"(addr) : "memory");
}
DEVI void stsm_x4(uint32_t addr, uint32_t r0, uint32_t r1, uint32_t r2, uint32_t r3) {
    asm volatile("stmatrix.sync.aligned.m8n8.x4.shared.b16 [%0], {%1, %2, %3, %4};"
        :: "r"(addr), "r"(r0), "r"(r1), "r"(r2), "r"(r3) : "memory");
}
DEVI void stsm_x4_t(uint32_t addr, uint32_t r0, uint32_t r1, uint32_t r2, uint32_t r3) {
    asm volatile("stmatrix.sync.aligned.m8n8.x4.trans.shared.b16 [%0], {%1, %2, %3, %4};"
        :: "r"(addr), "r"(r0), "r"(r1), "r"(r2), "r"(r3) : "memory");
}
DEVI uint32_t movm(uint32_t a) { uint32_t d; asm volatile("movmatrix.sync.aligned.m8n8.trans.b16 %0, %1;" : "=r"(d) : "r"(a)); return d; }
DEVI uint32_t pack2(float lo, float hi) { uint32_t d; asm("cvt.rn.bf16x2.f32 %0, %1, %2;" : "=r"(d) : "f"(hi), "f"(lo)); return d; }
DEVI float bf_lo(uint32_t v) { return __uint_as_float(v << 16); }
DEVI float bf_hi(uint32_t v) { return __uint_as_float(v & 0xffff0000u); }
DEVI float bf_round(float v) { return __bfloat162float(__float2bfloat16_rn(v)); }
DEVI uint32_t bf_mul2(uint32_t a, uint32_t b) { uint32_t d; asm("mul.rn.bf16x2 %0, %1, %2;" : "=r"(d) : "r"(a), "r"(b)); return d; }
DEVI uint32_t bf_add2(uint32_t a, uint32_t b) { uint32_t d; asm("add.rn.bf16x2 %0, %1, %2;" : "=r"(d) : "r"(a), "r"(b)); return d; }
DEVI uint32_t bf_sub2(uint32_t a, uint32_t b) { uint32_t d; asm("sub.rn.bf16x2 %0, %1, %2;" : "=r"(d) : "r"(a), "r"(b)); return d; }
DEVI uint4 lds128u(uint32_t a) { uint4 v; asm volatile("ld.shared.v4.u32 {%0, %1, %2, %3}, [%4];" : "=r"(v.x), "=r"(v.y), "=r"(v.z), "=r"(v.w) : "r"(a) : "memory"); return v; }
DEVI void sts128u(uint32_t a, uint32_t x, uint32_t y, uint32_t z, uint32_t w) { asm volatile("st.shared.v4.u32 [%0], {%1, %2, %3, %4};" :: "r"(a), "r"(x), "r"(y), "r"(z), "r"(w) : "memory"); }
DEVI uint2 lds64u(uint32_t a) { uint2 v; asm volatile("ld.shared.v2.u32 {%0, %1}, [%2];" : "=r"(v.x), "=r"(v.y) : "r"(a) : "memory"); return v; }
DEVI uint32_t ldg32u(const void* p) { uint32_t v; asm volatile("ld.global.nc.u32 %0, [%1];" : "=r"(v) : "l"(p) : "memory"); return v; }
DEVI void sts64(uint32_t a, float x, float y) { asm volatile("st.shared.v2.f32 [%0], {%1, %2};" :: "r"(a), "f"(x), "f"(y) : "memory"); }
DEVI void sts32(uint32_t a, uint32_t v) { asm volatile("st.shared.u32 [%0], %1;" :: "r"(a), "r"(v) : "memory"); }
DEVI uint32_t lds16(uint32_t a) { uint32_t v; asm volatile("ld.shared.u16 %0, [%1];" : "=r"(v) : "r"(a) : "memory"); return v; }
DEVI void cmul2(uint32_t& x, uint32_t& y, uint32_t c, uint32_t s, uint32_t n) {
    asm("{\n.reg .b32 t, u;\nmul.rn.bf16x2 t, %1, %4;\nmul.rn.bf16x2 u, %1, %2;\n"
        "fma.rn.bf16x2 %1, %0, %3, u;\nfma.rn.bf16x2 %0, %0, %2, t;\n}" : "+r"(x), "+r"(y) : "r"(c), "r"(s), "r"(n));
}
DEVI uint32_t neg2(uint32_t s) { uint32_t n; asm volatile("xor.b32 %0, %1, 0x80008000;" : "=r"(n) : "r"(s)); return n; }
DEVI void cmul2(uint32_t& x, uint32_t& y, uint32_t c, uint32_t s) { cmul2(x, y, c, s, neg2(s)); }
DEVI void cmul2c(uint32_t& x, uint32_t& y, uint32_t c, uint32_t s) { cmul2(x, y, c, neg2(s), s); }
DEVI void sts16(uint32_t a, float v) { asm volatile("st.shared.u16 [%0], %1;" :: "r"(a), "r"(pack2(v, v)) : "memory"); }

DEVI float2 cmul(float2 a, float2 b) { return make_float2(fmaf(a.x, b.x, -a.y * b.y), fmaf(a.x, b.y, a.y * b.x)); }
DEVI float2 cfma(float2 a, float2 b, float2 c) { return make_float2(fmaf(a.x, b.x, fmaf(-a.y, b.y, c.x)), fmaf(a.x, b.y, fmaf(a.y, b.x, c.y))); }

struct Params {
    const bf16 *lam_re, *lam_im, *log_dt, *dskip, *gate_w, *c_re, *c_im, *b_re, *b_im, *x;
    int swapB;
};

#define R8_POLL 8
#define R8B 1
#define SCB 32
#define C0 1
#define R8L 8
DEVI void radix8(uint32_t sb, bool inv, int w, int lane, int bar) {
    const uint64_t dg = make_desc(sb + OFF_G + (inv ? 512 : 0), 128, 256, 0), da = make_desc(sb + OFF_U, 16, 16384);
    float acc[2][64];
#pragma unroll
    for (int i = 0; i < 2; i++) {
        wgmma_fence();
#pragma unroll
        for (int j = 0; j < 8; j++) wgmma_n16<1>(acc[i] + 8 * j, da + 64 * (8 * i + j), dg);
        wgmma_commit();
    }
    const int kk = lane & 7, ch = 2 * w + ((lane >> 3) & 1);
    const uint32_t st = sb + OFF_U + (inv ? (lane >> 4) * 16384 + kk * 128 + ((ch ^ kk) << 4)
        : (kk & 1) * 16384 + (kk >> 2) * 2048 + (lane >> 4) * 1024 + (w >> 1) * 128 + ((((kk & 2) * 2 + ((ch & 3) ^ (kk >> 2) ^ (2 * (kk & 1)))) ^ (w >> 1)) << 4));
    uint32_t sa[4];
#pragma unroll
    for (int i = 0; i < 4; i++) sa[i] = inv ? (st ^ (i << 4)) + i * 1024 : (st ^ (i << 5)) + i * 256;
    uint32_t p[32];
#pragma unroll
    for (int i = 0; i < 2; i++) {
        if (i == 0) wgmma_wait<1>();
#pragma unroll
        for (int j = 0; j < 64; j++) asm volatile("" : "+f"(acc[i][j]) :: "memory");
#pragma unroll
        for (int j = 0; j < 32; j++) p[j] = pack2(acc[i][2 * j], acc[i][2 * j + 1]);
        if (i == 0) {
#pragma unroll
            for (int j = 0; j < 32; j++) asm volatile("" : "+r"(p[j]) :: "memory");
            wgmma_wait<0>();
            asm volatile("bar.sync %0, 128;" :: "r"(bar) : "memory");
        }
#pragma unroll
        for (int j = 0; j < 8; j++) stsm_x4_t(sa[j & 3] + (2 * i + (j >> 2)) * 4096, p[4 * j], p[4 * j + 1], p[4 * j + 2], p[4 * j + 3]);
    }
}

template<int N> DEVI void c_take(float (&acc)[32], uint32_t (&p)[16]) {
    wgmma_wait<N>();
#pragma unroll
    for (int i = 0; i < 32; i++) asm volatile("" : "+f"(acc[i]) :: "memory");
#pragma unroll
    for (int i = 0; i < 16; i++) p[i] = pack2(acc[2 * i], acc[2 * i + 1]);
}
DEVI void c_cols(float (&acc)[32], uint64_t df, uint64_t db) {
    wgmma_fence();
    wgmma_ss_n64<0>(acc, df, db);
#pragma unroll
    for (int s = 1; s < 4; s++) wgmma_ss_n64<1>(acc, df + 2 * s, db + 256 * s);
    wgmma_commit();
}

DEVI void phase_c(uint32_t sb, int ps, bool rot, int w, int lane, const uint4 (&tw)[4]) {
    const int warp = ps, bar = 5 + ps;
    PROFC(0);
    const uint32_t rb = sb + OFF_U + ps * 16384;
    const uint64_t df = make_desc(sb + OFF_F, 16, 1024), db = make_desc(rb, 16, 1024);
    float acc[2][32];
    c_cols(acc[0], df, db);
    c_cols(acc[1], df, db + 128);
    const int g = lane & 7, l3 = (lane >> 3) & 1, l4 = lane >> 4;
    uint32_t wf[2][4][4];
    const uint32_t wo = sb + OFF_W + (1 - ps) * 18432 + l4 * 9216 + g * 64 + ((w ^ (g >> 1)) << 4);
#pragma unroll
    for (int h = 0; h < 2; h++) {
        const uint32_t wm = wo + 4608 + (((rot ? 4 : 3) - 2 * h - l3) & 3) * 1152;
#pragma unroll
        for (int j = 0; j < 4; j++) ldsm_x4_t(wf[h][j], (j < 2 ? wo + (2 * h + l3) * 1152 : wm) + (j & 1) * 512);
    }
    uint32_t tn[8];
#pragma unroll
    for (int j = 0; j < 8; j++) tn[j] = neg2((j & 1) ? tw[j >> 1].w : tw[j >> 1].y);
    auto twiddle = [&](uint32_t& x, uint32_t& y, int j) { cmul2(x, y, (j & 1) ? tw[j >> 1].z : tw[j >> 1].x, (j & 1) ? tw[j >> 1].w : tw[j >> 1].y, tn[j]); };
#pragma unroll
    for (int h = 0; h < 2; h++) {
        uint32_t p[16], a[4][4];
        c_take<1>(acc[h], p);
        if (h == 0) PROFC(1);
#pragma unroll
        for (int i = 0; i < 8; i++) {
            twiddle(p[2 * i], p[2 * i + 1], (i & 3) ^ h);
            a[(i & 3) ^ h][i >> 2] = p[2 * i];
            a[(i & 3) ^ h][2 + (i >> 2)] = p[2 * i + 1];
        }
        wgmma_fence();
        wgmma_rs_n64<0>(acc[h], a[0], df + 4 * ps);
        wgmma_rs_n64<1>(acc[h], a[1], df + 4 * ps + 2);
        wgmma_rs_n64<1>(acc[h], a[2], df + 4 - 4 * ps);
        wgmma_rs_n64<1>(acc[h], a[3], df + 6 - 4 * ps);
        wgmma_commit();
    }
    PROFC(2);
#pragma unroll
    for (int h = 0; h < 2; h++) {
        uint32_t p[16], a[4][4];
        c_take<1>(acc[h], p);
#pragma unroll
        for (int i = 0; i < 8; i++) {
            const int j = i >> 1, r = i & 1;
            if (j < 2) cmul2(p[4 * j + r], p[4 * j + 2 + r], wf[h][j][r], wf[h][j][2 + r]);
            else cmul2c(p[4 * j + r], p[4 * j + 2 + r], wf[h][j][r], wf[h][j][2 + r]);
            a[j][r] = p[4 * j + 2 + r];
            a[j][2 + r] = p[4 * j + r];
        }
        wgmma_fence();
        wgmma_rs_n64<0>(acc[h], a[0], df);
#pragma unroll
        for (int j = 1; j < 4; j++) wgmma_rs_n64<1>(acc[h], a[j], df + 2 * j);
        wgmma_commit();
    }
    PROFC(3);
    const uint32_t xa = rb + w * 4096 + l4 * 1024 + g * 128 + (((4 * l3) ^ g) << 4);
#pragma unroll
    for (int h = 0; h < 2; h++) {
        uint32_t p[16];
        if (h) c_take<0>(acc[1], p); else c_take<1>(acc[0], p);
#pragma unroll
        for (int i = 0; i < 8; i++) twiddle(p[4 * (i >> 1) + (i & 1)], p[4 * (i >> 1) + 2 + (i & 1)], 4 + (i >> 1));
#pragma unroll
        for (int i = 0; i < 16; i++) asm volatile("" : "+r"(p[i]) :: "memory");
        if (h) fence_proxy_async_smem();
        asm volatile("bar.sync %0, 128;" :: "r"(bar) : "memory");
        if (h) c_cols(acc[0], df, db);
#pragma unroll
        for (int j = 0; j < 4; j++) stsm_x4((xa ^ (j << 4)) + h * 2048, p[4 * j], p[4 * j + 1], p[4 * j + 2], p[4 * j + 3]);
    }
    fence_proxy_async_smem();
    asm volatile("bar.sync %0, 128;" :: "r"(bar) : "memory");
    c_cols(acc[1], df, db + 128);
    PROFC(4);
    const uint32_t oa = rb + (4 * w + (g >> 1)) * 1024 + (1 - l3) * 512 + (((4 * (g & 1) + l4) ^ (4 - 4 * l3) ^ (g >> 1)) << 4);
#pragma unroll
    for (int h = 0; h < 2; h++) {
        uint32_t p[16];
        if (h) c_take<0>(acc[1], p);
        else {
            c_take<1>(acc[0], p);
#pragma unroll
            for (int i = 0; i < 16; i++) asm volatile("" : "+r"(p[i]) :: "memory");
            wgmma_wait<0>();
            asm volatile("bar.sync %0, 128;" :: "r"(bar) : "memory");
        }
#pragma unroll
        for (int i = 0; i < 4; i++) {
            const int r = 2 * h + (i >> 1);
            stsm_x4((oa ^ ((r ^ (2 * (i & 1))) << 4)) + r * 128, p[4 * i], p[4 * i + 1], p[4 * i + 2], p[4 * i + 3]);
        }
    }
    PROFC(5);
}

#define P_T 100
#define P_C 300
#define PACE_HA 200
#define PACE_HB 0
#define HN 4
#define PACE_V 100
#define VPOS 27
#define PACE_H 200
#define T_W0 2000
#define T_XS 2000
#define D_XS 0
#define P_XS 500
#define T_G 0
#define T_BA 1000
#define T_W1 3000
#define P_W 0
#define P_XE 600
#define P_R0 0
#define POL2 0
#define T_B2 4000
#define T_W 5000
#define PACE_U 200
#define PACE_L 0
#define T_FA 0
#define REG_M 216
#define REG_H 72
#define NS 4
#define SLOT_OF(k) (((k) + 1) % 4)
DEVI void tma_prefetch_4d(const CUtensorMap* map, int c0, int c1, int c2, int c3) {
    asm volatile("cp.async.bulk.prefetch.tensor.4d.L2.global [%0, {%1, %2, %3, %4}];" :: "l"(map), "r"(c0), "r"(c1), "r"(c2), "r"(c3) : "memory");
}
DEVI void bar_sync(int id, int n) { asm volatile("bar.sync %0, %1;" :: "r"(id), "r"(n) : "memory"); }
DEVI void bar_arrive(int id, int n) { asm volatile("bar.arrive %0, %1;" :: "r"(id), "r"(n) : "memory"); }
DEVI uint4 ldg128(const void* p) { uint4 v; asm volatile("ld.global.nc.v4.u32 {%0, %1, %2, %3}, [%4];" : "=r"(v.x), "=r"(v.y), "=r"(v.z), "=r"(v.w) : "l"(p)); return v; }
DEVI uint32_t ldg16(const void* p) { uint32_t v; asm volatile("ld.global.nc.u16 %0, [%1];" : "=r"(v) : "l"(p)); return v; }
DEVI uint32_t bf_fma2(uint32_t a, uint32_t b, uint32_t c) { uint32_t d; asm("fma.rn.bf16x2 %0, %1, %2, %3;" : "=r"(d) : "r"(a), "r"(b), "r"(c)); return d; }
DEVI void bulk_wait_read() { asm volatile("cp.async.bulk.wait_group.read 0;" ::: "memory"); }

DEVI float lds32f(uint32_t a) { float v; asm volatile("ld.shared.f32 %0, [%1];" : "=f"(v) : "r"(a) : "memory"); return v; }
DEVI uint32_t mbar_test(uint32_t bar, uint32_t parity) {
    uint32_t ok;
    asm volatile("{\n.reg .pred p;\nmbarrier.test_wait.parity.shared::cta.b64 p, [%1], %2;\nselp.u32 %0, 1, 0, p;\n}" : "=r"(ok) : "r"(bar), "r"(parity) : "memory");
    return ok;
}
template<int TA> DEVI void ring_steps(float (&acc)[2][64], uint32_t sb, uint32_t fb, int n, int ns, int& s, uint32_t& phm, bool first, bool lead, uint32_t rel, int first_bar, int last_bar, int pi) {
    const uint64_t da0 = TA ? make_desc(sb, 4096, 512, 2) : make_desc(sb, 16, 1024), db0 = make_desc(sb + 16384, 16, 1024);
    uint32_t eb = sb + OFF_BAR + 8 * BAR_HR;
    mbar_wait(fb + 8 * s, (phm >> s) & 1);
    if (first_bar) bar_sync(first_bar, 256);
#pragma unroll 1
    for (;;) {
        PROFK(pi++);
        const uint64_t da = da0 + (uint32_t)(s * 2048), db = db0 + (uint32_t)(s * 2048);
        wgmma_fence();
#pragma unroll
        for (int j = 0; j < 4; j++) {
            wgmma_n128<TA, 0>(acc[0], da + (TA ? 64 : 2) * j, db + 2 * j, j || !first);
            wgmma_n128<TA, 0>(acc[1], da + 512 + (TA ? 64 : 2) * j, db + 2 * j, j || !first);
        }
        wgmma_commit();
        first = false;
        phm ^= 1u << s;
        if (--n == 0) break;
        const uint32_t en = rel + 8 * s;
        if (++s == ns) s = 0;
        const uint32_t ok = mbar_test(fb + 8 * s, (phm >> s) & 1);
        wgmma_wait<1>();
        if (lead) mbar_arrive(eb);
        eb = en;
        if (!ok) mbar_wait(fb + 8 * s, (phm >> s) & 1);
        __syncwarp();
    }
    if (last_bar) bar_arrive(last_bar, 256);
    wgmma_wait<1>();
    if (lead) mbar_arrive(eb);
}

__global__ void __cluster_dims__(2, 1, 1) __launch_bounds__(384, 1)
fused_kernel(const __grid_constant__ CUtensorMap mapB, const __grid_constant__ CUtensorMap mapX,
             const __grid_constant__ CUtensorMap mapXs, const __grid_constant__ CUtensorMap mapU0,
             const __grid_constant__ CUtensorMap mapU2, const __grid_constant__ CUtensorMap mapXe,
             const __grid_constant__ CUtensorMap mapCre, const __grid_constant__ CUtensorMap mapCim,
             const __grid_constant__ CUtensorMap mapV, const __grid_constant__ CUtensorMap mapO,
             const __grid_constant__ CUtensorMap mapWr, const __grid_constant__ CUtensorMap mapWi,
             const __grid_constant__ CUtensorMap mapH,
             const __grid_constant__ Params P) {
    extern __shared__ __align__(1024) uint8_t sm[];
    const uint32_t sb = smem_u32(sm);
    const uint32_t bars = sb + OFF_BAR;
    const unsigned cl = blockIdx.x >> 1;
    const int role = cl < 4 ? 32 + 8 * cl : cl < 36 ? ((cl - 4) & 24) + ((cl - 5) & 7) : cl < 64 ? 33 + (cl - 36) / 7 * 8 + (cl - 30) % 7 : cl;
    const int b = role * 2 + (blockIdx.x & 1), tid = threadIdx.x, warp = __shfl_sync(0xffffffffu, tid >> 5, 0), lane = tid & 31;
    const bool main_cta = b < 128;
    if (b == 129) return;
    const int rp = (b >> 1) & 3, mq = ((b >> 3) & 2) + (b & 1), dt = ((b >> 1) & 4) + (b >> 5), tc = 4 * rp + mq;
    const int cls = b == 128 ? 128 : (b & 31) ? (b & 31) + 64 * (b >> 5) : (b == 64 ? 32 : b == 32 ? 64 : b);
    if (warp != 8 && elect()) {
        if (warp == 11) PROFG(0);
        const int u = warp - (warp > 8);
        asm volatile("prefetch.tensormap [%0];" :: "l"(&mapB + 2 + u) : "memory");
        mbar_init(bars + 8 * (5 + u), 1);
        mbar_init(bars + 8 * (16 + u), u ? 4 : 1);
        mbar_init(bars + 8 * (27 + u), u < 1 ? 4 : u == 6 ? 8 : (u == 7 || u == 8) ? 64 : 1);
        fence_barrier_init();
        fence_proxy_async_smem();
    }
    __syncwarp();
    const bool real_cls = (cls & 127) == 0;
    const int t = tid & 127;
    auto load_epoch = [&]() {
        unsigned e;
        asm volatile("ld.relaxed.gpu.global.u32 %0, [%1];" : "=r"(e) : "l"(&g_cnt[CNT_EPOCH * CS]));
        return e + 1;
    };
    const int g = lane >> 2, q = lane & 3;

    if (warp < 8) {
        reg_alloc<REG_M>();
        const int wg = warp >> 2, w = warp & 3;
        if (tid == 0) PROFX(94);
        bar_sync(0, 384);
        if (tid == 224) PROFG(8);
        auto kept = [&](int i) { uint64_t v; asm volatile("ld.volatile.shared.u64 %0, [%1];" : "=l"(v) : "r"(sb + OFF_KEPT + 8 * i) : "memory"); return v; };
        const uint32_t fb = bars + 8 * (BAR_FULL + 5 * wg);
        uint32_t phm = 0;
        const bool lead = lane == 0;
        const uint32_t rel = bars + 8 * BAR_EMPTY;
        if (wg) {
            {
                const int pp = (dt * 64 + 8 * (t & 64) + (t & 63)) & 1023;
                const uint32_t lr_ = ldg16(P.lam_re + pp), li_ = ldg16(P.lam_im + pp), ld_ = ldg16(P.log_dt + pp);
                const unsigned epoch = load_epoch();
                if (t < 64 && main_cta) g_agg[rp * 2048 + (dt + (t >> 5) * 8) * 128 + lane * 4 + mq] = make_uint4(0u, 0u, 0u, 0u);
                if (t < 4) asm volatile("st.shared.u64 [%0], %1;" :: "r"(sb + OFF_KEPT + 8 * lane),
                    "l"(lane == 0 ? (P.swapB ? 255ull : 127ull) | ((uint64_t)epoch << 32) : lane == 1 ? (uint64_t)g_agg : lane == 2 ? (uint64_t)(c_tab + 10240) : (uint64_t)&mapB) : "memory");
                const float lr = bf_lo(lr_), li = bf_lo(li_);
                const float dl = bf_round(expf(bf_lo(ld_)));
                const float mag = expf(dl * lr);
                float sn, cs; sincospif(dl * li * 0.31830988618379067f, &sn, &cs);
                const float2 l1 = make_float2(mag * cs, mag * sn);
                const float inv = 1.f / (lr * lr + li * li);
                const float2 cf = cmul(make_float2(l1.x - 1.f, l1.y), make_float2(lr * inv, -li * inv));
                sts128u(sb + OFF_K + 16 * t, __float_as_uint(l1.x), __float_as_uint(P.swapB ? -l1.y : l1.y), __float_as_uint(cf.x), __float_as_uint(cf.y));
                if (tid == 128) PROFX(92);
            }
            {
                const int kk = (t >> 3) & 7, r = t & 7;
                float sn, cs;
                sincospif((float)(((cls + 256 * kk) * r) & 2047) * (1.f / 1024.f), &sn, &cs);
                sn *= 1.f / 1024.f; cs *= 1.f / 1024.f;
                const uint32_t gf = sb + OFF_G + kk * 16 + r * 2, gi = sb + OFF_G + 512 + r * 16 + (kk & 1) * 128 + (kk & 6);
                if (t < 64) {
                    sts16(gf, cs); sts16(gf + 128, real_cls ? 0.f : sn); sts16(gf + 256, -sn); sts16(gf + 384, real_cls ? 0.f : cs);
                    sts16(gi, cs); sts16(gi + 8, -sn); sts16(gi + 256, sn); sts16(gi + 264, cs);
                }
            }
            if (main_cta) {
                uint32_t fa[16][4];
                pause(T_FA);
#pragma unroll
                for (int i = 0; i < 16; i++) {
                    asm volatile("ld.global.nc.L1::no_allocate.v4.u32 {%0, %1, %2, %3}, [%4];" : "=r"(fa[i][0]), "=r"(fa[i][1]), "=r"(fa[i][2]), "=r"(fa[i][3]) : "l"((const uint4*)c_tab + i * 128 + t));
                }
                if (t == 0) PROFX(91);
                const uint32_t ua = sb + OFF_U + (lane >> 4) * 4096 + (8 * w + (lane & 7)) * 128 + ((((lane >> 3) & 1) ^ (lane & 7)) << 4);
                float acc[4][32];
                const uint64_t db = make_desc(sb + OFF_U, 8192, 1024);
                uint32_t x[4][8], y[4][8];
                float gp[4][4];
#pragma unroll
                for (int m = 0; m < 6; m++) {
                    if (m >= 2) {
                        const int n = m - 2;
                        if (m < 5) wgmma_wait<1>(); else wgmma_wait<0>();
#pragma unroll
                        for (int i = 0; i < 32; i++) asm volatile("" : "+f"(acc[n][i]) :: "memory");
                        asm volatile("" : "+f"(gp[n][0]), "+f"(gp[n][2]) :: "memory");
#pragma unroll
                        for (int j = 0; j < 8; j++) { x[n][j] = pack2(acc[n][4 * j], acc[n][4 * j + 1]); y[n][j] = pack2(acc[n][4 * j + 2], acc[n][4 * j + 3]); }
                    }
                    if (m < 4) {
                        mbar_wait(bars + 8 * (BAR_XC + m), 0);
                        if (t == 0 && m == 3) PROF(8);
                        wgmma_fence();
                        wgmma_rs_n64<0, 1>(acc[m], fa[4 * m], db + 512 * m);
#pragma unroll
                        for (int j = 1; j < 4; j++) wgmma_rs_n64<1, 1>(acc[m], fa[4 * m + j], db + 512 * m + 128 * j);
#pragma unroll
                        for (int j = 0; j < 4; j++) wgmma_n8(gp[m], make_desc(sb + OFF_U, 16, 1024) + 512 * m + 2 * j, make_desc(sb + OFF_GW, 16, 1024) + 2 * j, j);
                        wgmma_commit();
                    }
                }
                if (t < 4) {
#pragma unroll
                    for (int j = 0; j < 8; j++) {
                        const uint32_t s0 = bf_add2(x[0][j], x[2][j]), s2 = bf_add2(x[1][j], x[3][j]), ty = bf_sub2(y[1][j], y[3][j]), sy = bf_add2(y[1][j], y[3][j]);
                        const uint32_t b0 = y[0][j], b2 = y[2][j];
                        y[1][j] = bf_sub2(x[3][j], x[1][j]); x[1][j] = bf_sub2(x[0][j], x[2][j]);
                        x[0][j] = bf_add2(s0, s2); y[0][j] = bf_sub2(s0, s2);
                        x[2][j] = bf_add2(b0, ty); y[2][j] = bf_add2(sy, b2) ^ 0x80008000u;
                        x[3][j] = bf_sub2(b0, ty); y[3][j] = bf_sub2(b2, sy);
                    }
                } else {
#pragma unroll
                    for (int j = 0; j < 8; j++) {
                        const uint32_t s0x = bf_add2(x[0][j], x[2][j]), s1x = bf_sub2(x[0][j], x[2][j]), s2x = bf_add2(x[1][j], x[3][j]), tx = bf_sub2(x[1][j], x[3][j]);
                        const uint32_t s0y = bf_add2(y[0][j], y[2][j]), s1y = bf_sub2(y[0][j], y[2][j]), s2y = bf_add2(y[1][j], y[3][j]), ty = bf_sub2(y[1][j], y[3][j]);
                        x[0][j] = bf_add2(s0x, s2x); y[0][j] = bf_add2(s0y, s2y);
                        x[1][j] = bf_add2(s1x, ty); y[1][j] = bf_sub2(s1y, tx);
                        x[2][j] = bf_sub2(s0x, s2x); y[2][j] = bf_sub2(s0y, s2y);
                        x[3][j] = bf_sub2(s1x, ty); y[3][j] = bf_add2(s1y, tx);
                    }
                }
                helper_sync();
                if (q == 0) {
#pragma unroll
                    for (int i = 0; i < 2; i++)
                        sts128u(sb + OFF_GW + (16 * w + 8 * i + g) * 16, __float_as_uint(gp[0][2 * i]), __float_as_uint(gp[1][2 * i]), __float_as_uint(gp[2][2 * i]), __float_as_uint(gp[3][2 * i]));
                }
#pragma unroll
                for (int c = 0; c < 4; c++)
#pragma unroll
                    for (int j = 0; j < 8; j += 2) stsm_x4((ua ^ (j << 4)) + c * 8192, x[c][j], x[c][j + 1], y[c][j], y[c][j + 1]);
                if (t == 0) PROF(21);
            }
            fence_proxy_async_smem();
            __syncwarp();
            if (lane == 0) mbar_arrive(bars + 8 * BAR_S1);
        }
        uint4 tw[4];
        auto load_tw = [&]() {
            const uint4* twp = (const uint4*)kept(2) + t;
#pragma unroll
            for (int i = 0; i < 4; i++) tw[i] = ldg128(twp + (i < 2 ? i ^ wg : i & 1) * 128);
        };
        {
            float acc[2][64];
            float2 lam8[2], lam32[2], lam64[2], wq[2], w4[2], l32q[2], ex[2];
            float2 ag[2][4];
            if (main_cta) {
                int sp = wg * SLOT_OF(16);
                ring_steps<0>(acc, sb, fb, 16, 5 - wg, sp, phm, true, lead, rel, 2 * wg, 2 + wg, 16 * wg);
                mbar_wait(bars + 8 * BAR_S1, 0);
                const uint4* ap = (const uint4*)kept(1) + (((tc - 1 - q) >> 2) * 2048 + (dt + 8 * wg) * 128 + t);
                const uint64_t k0 = kept(0);
                const uint32_t fl = (uint32_t)k0, tag = ((uint32_t)(k0 >> 32) & 7) | 8;
                const bool swapB = fl & 128;
                float2 lam1[2], coef[2];
#pragma unroll
                for (int i = 0; i < 2; i++) {
                    const uint4 kv = lds128u(sb + OFF_K + (64 * wg + 32 * i + (t >> 2)) * 16);
                    lam1[i] = make_float2(__uint_as_float(kv.x), __uint_as_float(kv.y));
                    coef[i] = make_float2(__uint_as_float(kv.z), __uint_as_float(kv.w));
                    float2 z = cmul(lam1[i], lam1[i]);
                    z = cmul(z, z);
                    lam8[i] = cmul(z, z);
                    z = cmul(lam8[i], lam8[i]);
                    lam32[i] = cmul(z, z); lam64[i] = cmul(lam32[i], lam32[i]);
                    const float2 l128 = cmul(lam64[i], lam64[i]), l256 = cmul(l128, l128), one = make_float2(1.f, 0.f);
                    w4[i] = cmul(l256, l256);
                    wq[i] = cmul(((tc - 1 - q) & 1) ? l128 : one, ((tc - 1 - q) & 2) ? l256 : one);
                    l32q[i] = cmul((q & 1) ? lam32[i] : one, (q & 2) ? lam64[i] : one);
                    asm volatile("" : "+f"(w4[i].x), "+f"(w4[i].y), "+f"(wq[i].x), "+f"(wq[i].y), "+f"(l32q[i].x), "+f"(l32q[i].y));
                }
                sched_fence();
                wgmma_wait_all(acc[0]);
#pragma unroll
                for (int o = 0; o < 64; o++) asm volatile("" : "+f"(acc[1][o]) :: "memory");
                if (lead) mbar_arrive(rel + 8 * (sp));
                if (tid == 0) PROF(3);
                if (tid == 128) PROF(25);
                if (tid == 224) PROFG(12);
                float2 v[2];
#pragma unroll
                for (int c = 0; c < 8; c++) ag[c >> 2][c & 3] = make_float2(acc[c >> 2][16 * (c & 3)], acc[c >> 2][16 * (c & 3) + 2]);
#pragma unroll
                for (int r = 1; r < 8; r++)
#pragma unroll
                    for (int c = 0; c < 8; c++) {
                        const int i = c >> 2, o = 16 * (c & 3) + 4 * (r >> 1) + (r & 1);
                        ag[i][c & 3] = cfma(lam1[i], ag[i][c & 3], make_float2(acc[i][o], acc[i][o + 2]));
                    }
#pragma unroll
                for (int i = 0; i < 2; i++) {
                    v[i] = ag[i][0];
#pragma unroll
                    for (int c = 1; c < 4; c++) v[i] = cfma(lam8[i], v[i], ag[i][c]);
                    float2 n = make_float2(__shfl_up_sync(0xffffffffu, v[i].x, 1, 4), __shfl_up_sync(0xffffffffu, v[i].y, 1, 4));
                    if (q >= 1) v[i] = cfma(lam32[i], n, v[i]);
                    n = make_float2(__shfl_up_sync(0xffffffffu, v[i].x, 2, 4), __shfl_up_sync(0xffffffffu, v[i].y, 2, 4));
                    if (q >= 2) v[i] = cfma(lam64[i], n, v[i]);
                }
                if (q == 3 && tc < 15) {
                    asm volatile("{\n.reg .b64 a, b;\nmov.b64 a, {%1, %2};\nmov.b64 b, {%3, %4};\nst.relaxed.gpu.global.v2.b64 [%0], {a, b};\n}"
                        :: "l"(ap + (2045 + mq)), "r"((__float_as_uint(v[0].x) & ~15u) | tag), "r"(__float_as_uint(v[0].y)),
                           "r"((__float_as_uint(v[1].x) & ~15u) | tag), "r"(__float_as_uint(v[1].y)) : "memory");
                }
                PROFS(72 + 8 * wg);
                sched_fence();
                {
                    float m00[2], m01[2], m10[2], m11[2];
                    auto scale = [&](int i, float& x, float& y) { const float u = fmaf(m00[i], x, m01[i] * y); y = fmaf(m10[i], x, m11[i] * y); x = u; };
#pragma unroll
                    for (int i = 0; i < 2; i++) {
                        ex[i] = make_float2(__shfl_up_sync(0xffffffffu, v[i].x, 1, 4), __shfl_up_sync(0xffffffffu, v[i].y, 1, 4));
                        if (q == 0) ex[i] = make_float2(0.f, 0.f);
                        const float cx = coef[i].x, cy = coef[i].y;
                        m00[i] = cx; m01[i] = -cy; m10[i] = -cy; m11[i] = -cx;
                        if (swapB) { m00[i] = -cy; m01[i] = cx; m10[i] = -cx; m11[i] = -cy; }
                        scale(i, ex[i].x, ex[i].y);
                        scale(i, l32q[i].x, l32q[i].y);
                        if (!swapB) { lam1[i].y = -lam1[i].y; lam8[i].y = -lam8[i].y; }
#pragma unroll
                        for (int o = 0; o < 64; o += 4) {
                            scale(i, acc[i][o], acc[i][o + 2]); scale(i, acc[i][o + 1], acc[i][o + 3]);
                            if ((o + 4) % SCB == 0) {
#pragma unroll
                                for (int u = o + 4 - SCB; u < o + 4; u++) asm volatile("" : "+f"(acc[i][u]));
                                sched_fence();
                            }
                        }
#pragma unroll
                        for (int c = 0; c < 3; c++) scale(i, ag[i][c].x, ag[i][c].y);
                    }
                }
                PROFS(73 + 8 * wg);
                uint4 rr[4];
#pragma unroll
                for (int n = 0; n < 4; n++) rr[n] = make_uint4(tag, 0u, tag, 0u);
                auto poll = [&]() {
#pragma unroll
                    for (int n = 0; n < 4; n++)
                        asm volatile("{\n.reg .b64 a, b;\n.reg .pred p;\nsetp.lt.s32 p, %5, %6;\nmov.b64 a, {%0, %1};\nmov.b64 b, {%2, %3};\n"
                                     "@p ld.relaxed.gpu.global.v2.b64 {a, b}, [%4];\nmov.b64 {%0, %1}, a;\nmov.b64 {%2, %3}, b;\n}"
                            : "+r"(rr[n].x), "+r"(rr[n].y), "+r"(rr[n].z), "+r"(rr[n].w) : "l"(ap - 2048 * n), "r"(4 * n), "r"(tc - q) : "memory");
                };
                poll();
#pragma unroll 1
                for (unsigned n = 0; n < SPIN_LIMIT; n++) {
                    uint32_t bad = 0;
#pragma unroll
                    for (int j = 0; j < 4; j++) bad |= (rr[j].x ^ tag) | (rr[j].z ^ tag);
                    if (!__any_sync(0xffffffffu, bad & 15)) break;
                    if (n < 3) PROFS(74 + 8 * wg + n);
                    poll();
                }
                float2 part[2] = {make_float2(__uint_as_float(rr[3].x), __uint_as_float(rr[3].y)), make_float2(__uint_as_float(rr[3].z), __uint_as_float(rr[3].w))};
#pragma unroll
                for (int n = 2; n >= 0; n--) {
                    part[0] = cfma(w4[0], part[0], make_float2(__uint_as_float(rr[n].x), __uint_as_float(rr[n].y)));
                    part[1] = cfma(w4[1], part[1], make_float2(__uint_as_float(rr[n].z), __uint_as_float(rr[n].w)));
                }
#pragma unroll
                for (int i = 0; i < 2; i++) {
                    part[i] = cmul(wq[i], part[i]);
                    part[i].x += __shfl_xor_sync(0xffffffffu, part[i].x, 1); part[i].y += __shfl_xor_sync(0xffffffffu, part[i].y, 1);
                    part[i].x += __shfl_xor_sync(0xffffffffu, part[i].x, 2); part[i].y += __shfl_xor_sync(0xffffffffu, part[i].y, 2);
                    if (!swapB) part[i].y = -part[i].y;
                    ex[i] = cfma(l32q[i], part[i], ex[i]);
#pragma unroll
                    for (int c = 0; c < 4; c++) { const float2 n = cfma(lam8[i], ex[i], ag[i][c]); ag[i][c] = ex[i]; ex[i] = n; }
                }
                if (t == 0) PROF(4 + 25 * wg);
                const uint32_t hs = sb + OFF_HS + w * 512 + ((lane * 16) ^ ((lane << 1) & 48));
#pragma unroll
                for (int i = 0; i < 2; i++) {
                    if (fl & (4 << i)) {
#pragma unroll
                        for (int r = 0; r < 8; r++)
#pragma unroll
                            for (int c = 0; c < 4; c++) {
                                const int o = 16 * c + 4 * (r >> 1) + (r & 1);
                                ag[i][c] = cfma(lam1[i], ag[i][c], make_float2(acc[i][o], acc[i][o + 2]));
                                acc[i][o] = ag[i][c].x; acc[i][o + 2] = ag[i][c].y;
                            }
                    }
                    if (i) {
                        fence_proxy_async_smem();
                        __syncwarp();
                        if (lane == 0) mbar_arrive(bars + 8 * BAR_HW);
                    }
                    mbar_wait(bars + 8 * (wg ? (i ? BAR_WR : BAR_HD) : BAR_EMPTY + 4), 0);
#pragma unroll
                    for (int z = 0; z < 8; z++) {
                        const float* a = &acc[i][2 * z];
                        sts128u(hs + i * (16384 + wg * 18432) + (z & 1) * 8192 + (z >> 1) * 2048, pack2(a[0], a[16]), pack2(a[32], a[48]), pack2(a[1], a[17]), pack2(a[33], a[49]));
                    }
                }
                fence_proxy_async_smem();
                __syncwarp();
                if (lane == 0) mbar_arrive(bars + 8 * (BAR_HW + 1));
                load_tw();
                if (t == 0) PROF(5 + 25 * wg);
            } else {
                mbar_wait(bars + 8 * BAR_S1, 0);
                load_tw();
            }
        }
        if (wg) mbar_wait(bars + 8 * BAR_WR, 0);
#pragma unroll 1
        for (int ps = wg; ps < 1 + 2 * wg; ps++) {
            if (ps != 1) {
                mbar_wait(bars + (ps ? 8 * BAR_CD : 8 * BAR_U), 0);
                if (t == 0) PROF(ps ? 7 : 23);
                radix8(sb, ps, w, lane, 5 + wg);
                if (t == 0) PROF(ps ? 24 : 22);
                if (ps) break;
                fence_proxy_async_smem();
                bar_sync(5, 128);
            }
            mbar_wait(bars + 8 * (BAR_C + ps), 0);
            phase_c(sb, ps, b + ps == 0, w, lane, tw);
            fence_proxy_async_smem();
            __syncwarp();
            if (lane == 0) {
                mbar_arrive(bars + 8 * BAR_CD);
                if (!wg) mbar_arrive(bars + 8 * BAR_WR);
            }
        }
        const int m0 = 64 * mq + 8 * w;
        if (wg == 0) {
            if (main_cta) {
                float acc[2][64];
                int s = SLOT_OF(32);
#pragma unroll 1
                for (int sg = 0;; sg++) {
                    ring_steps<1>(acc, sb, fb, sg ? 28 - VPOS : VPOS, NS, s, phm, !sg, lead, rel, sg ? 0 : 3, 0, 32 + sg * VPOS);
                    if (sg) break;
                    wgmma_wait<0>();
                    if (lead) mbar_arrive(rel + 8 * (s));
                    __syncwarp();
                    s = SLOT_OF(36 + VPOS);
                }
#pragma unroll
                for (int i = 0; i < 2; i++) {
#pragma unroll
                    for (int k = 0; k < 4; k++) {
                        const int s = SLOT_OF(64 + k);
                        if (i == 0) { mbar_wait(fb + 8 * s, (phm >> s) & 1); PROFK(60 + k); }
                        const uint64_t da = make_desc(sb + s * SLOT + i * 8192, 4096, 512, 2), db = make_desc(sb + s * SLOT + 16384, 16, 1024);
                        wgmma_fence();
#pragma unroll
                        for (int j = 0; j < 4; j++) wgmma_n128<1, 0>(acc[i], da + 64 * j, db + 2 * j, 1);
                        if (i == 0 && k == 0) {
                            wgmma_commit();
                            wgmma_wait<1>();
                            if (lead) mbar_arrive(rel + 8 * (SLOT_OF(63)));
                            __syncwarp();
                        }
                    }
                    wgmma_commit();
                }
                bar_sync(4, 256);
                const CUtensorMap* maps = (const CUtensorMap*)kept(3);
                float sc[2][2];
#pragma unroll
                for (int i = 0; i < 4; i++) sc[i >> 1][i & 1] = lds32f(sb + OFF_SC + (8 * w + 32 * (i >> 1) + 4 * (i & 1) + (g & 3)) * 8 + (g >> 2) * 4);
                const uint32_t rw = 2 * (g & 3) + (g >> 2);
                const uint32_t ob = sb + OFF_HS + w * 2048, oa = ob + rw * 128 + (((q >> 1) ^ rw) << 4) + (q & 1) * 8;
                const uint32_t ea = sb + OFF_U + (16 * w + (lane & 15)) * 128 + (((lane >> 4) ^ (lane & 7) ^ ((lane >> 1) & 4)) << 4);
#pragma unroll
                for (int i = 0; i < 2; i++) {
                    uint32_t e[8][4];
#pragma unroll
                    for (int j = 0; j < 8; j++) ldsm_x4(e[j], (ea ^ ((j & 3) << 5)) + (j >> 2) * 16384 + i * 8192);
                    if (i) wgmma_wait<0>(); else wgmma_wait<1>();
#pragma unroll
                    for (int o = 0; o < 64; o++) asm volatile("" : "+f"(acc[i][o]) :: "memory");
                    if (tid == 0) PROF(17 + i);
                    if (tid == 96 && i) PROFG(20);
#pragma unroll
                    for (int c = 0; c < 4; c++) {
#pragma unroll
                        for (int j = 0; j < 8; j++) {
                            const int o = 16 * c + 2 * j;
                            const uint32_t ev = e[2 * c + (j >> 2)][j & 3];
                            sts64((oa ^ ((j >> 1) << 5)) + c * 8192 + i * 32768 + (j & 1) * 1024,
                                  fmaf(sc[i][j & 1], acc[i][o], bf_lo(ev)), fmaf(sc[i][j & 1], acc[i][o + 1], bf_hi(ev)));
                        }
                        fence_proxy_async_smem();
                        __syncwarp();
                        if (elect()) tma_store_4d(maps + 9, ob + c * 8192 + i * 32768, 128 * dt + 32 * c, 0, rp, m0 + 32 * i);
                    }
                }
                if (elect()) {
                    bulk_commit();
                    bulk_wait_read();
                }
                if (tid == 0) PROF(19);
                if (tid == 96) { PROF(20); PROFG(4); }
            }
        } else {
            fence_proxy_async_smem();
            __syncwarp();
            if (lane == 0) mbar_arrive(bars + 8 * BAR_VW);
            __syncwarp();
            if (tid == 224) PROFG(16);
            if (main_cta) {
                uint32_t sk[2][32], gd[2][2];
                {
                    float gs[16];
                    uint32_t dk[16];
#pragma unroll
                    for (int j = 0; j < 16; j++) gs[j] = __ldcg(g_gp + (32 * rp + (t >> 6) * 16 + j) * 256 + 64 * mq + (t & 63));
#pragma unroll
                    for (int j = 0; j < 16; j++) dk[j] = ldg32u(P.dskip + 128 * dt + 8 * j + 2 * q);
#pragma unroll
                    for (int j = 0; j < 4; j++) gs[j] = (gs[j] + gs[j + 4]) + (gs[j + 8] + gs[j + 12]);
                    gs[0] = (gs[0] + gs[1]) + (gs[2] + gs[3]);
                    const float gg = bf_round(__fdividef(1.f, 1.f + __expf(-bf_round(gs[0])))), og = bf_round(1.f - gg);
                    const uint32_t go = (t & 63) * 8 + (t >> 6) * 4;
                    sts32(sb + OFF_SC + go, __float_as_uint(2.f * og));
                    sts32(sb + OFF_K + go, pack2(gg, og));
                    bar_sync(6, 128);
                    const uint2 g0 = lds64u(sb + OFF_K + (16 * w + g) * 8), g1 = lds64u(sb + OFF_K + (16 * w + 8 + g) * 8);
                    mbar_wait(bars + 8 * BAR_X, 0);
                    const uint32_t xa = sb + OFF_HS + (16 * w + (lane & 15)) * 128 + (((lane >> 4) ^ (lane & 7)) << 4);
#pragma unroll
                    for (int e = 0; e < 2; e++) {
                        const uint32_t u0 = e ? g0.y : g0.x, u1 = e ? g1.y : g1.x, o0 = __byte_perm(u0, 0, 0x3232), o1 = __byte_perm(u1, 0, 0x3232);
                        gd[e][0] = __byte_perm(u0, 0, 0x1010); gd[e][1] = __byte_perm(u1, 0, 0x1010);
#pragma unroll
                        for (int j = 0; j < 8; j++) {
                            uint32_t x[4];
                            ldsm_x4(x, (xa ^ ((j & 3) << 5)) + e * 8192 + (j >> 2) * 34816);
#pragma unroll
                            for (int c = 0; c < 4; c++) {
                                sk[e][4 * j + c] = bf_mul2(bf_mul2(x[c], dk[2 * j + (c >> 1)]), (c & 1) ? o1 : o0);
                                asm volatile("" : "+r"(sk[e][4 * j + c]));
                            }
                        }
                    }
                    if (t == 0) PROFX(95);
                }
                float acc[2][64];
                mbar_wait(bars + 8 * BAR_T, 1);
#pragma unroll
                for (int k = 0; k < 4; k++) {
                    const int s = SLOT_OF(32 + VPOS + k);
                    mbar_wait(fb + 8 * s, (phm >> s) & 1);
                    PROFK(64 + k);
                    const uint64_t da = make_desc(sb + OFF_U + k * 8192, 4096, 512, 2), db = make_desc(sb + s * SLOT, 8192, 1024);
                    wgmma_fence();
#pragma unroll
                    for (int j = 0; j < 4; j++) {
                        wgmma_n128<1, 1>(acc[0], da + 64 * j, db + 128 * j, (k | j) != 0);
                        wgmma_n128<1, 1>(acc[1], da + 64 * j, db + 1024 + 128 * j, (k | j) != 0);
                    }
                    wgmma_commit();
                    if (k) {
                        wgmma_wait<1>();
                        if (lead) mbar_arrive(rel + 8 * (SLOT_OF(31 + VPOS + k)));
                        __syncwarp();
                    }
                }
                wgmma_wait_all(acc[0]);
#pragma unroll
                for (int o = 0; o < 64; o++) asm volatile("" : "+f"(acc[1][o]) :: "memory");
                if (lead) mbar_arrive(rel + 8 * (SLOT_OF(35 + VPOS)));
                if (t == 0) PROF(15);
                bar_sync(6, 128);
                const uint32_t ea = sb + OFF_U + (32 * w + 2 * (lane & 12) + (lane & 3)) * 128 + (((lane >> 4) ^ (lane & 7)) << 4);
#pragma unroll
                for (int e = 0; e < 2; e++)
#pragma unroll
                    for (int j = 0; j < 8; j++) {
                        uint32_t ev[4];
#pragma unroll
                        for (int c = 0; c < 4; c++) ev[c] = bf_fma2(pack2(acc[e][8 * j + 2 * c], acc[e][8 * j + 2 * c + 1]), gd[e][c & 1], sk[e][4 * j + c]);
                        stsm_x4((ea ^ ((j & 3) << 5) ^ (e << 6)) + e * 512 + (j >> 2) * 16384, ev[0], ev[1], ev[2], ev[3]);
                    }
                bar_arrive(4, 256);
                if (t == 0) PROF(16);
            }
            if (t == 0) {
                const unsigned old = atomicAdd(&g_cnt[CNT_DONE * CS], 1u);
                if (old == 128) { g_cnt[CNT_DONE * CS] = 0; g_cnt[CNT_EPOCH * CS] = (uint32_t)(kept(0) >> 32); }
            }
        }
    } else {
        reg_dealloc<REG_H>();
        const int w = warp - 8;
        if (w == 0) {
            if (elect()) {
                PROF(0);
#pragma unroll
                for (int i = 0; i < 5; i++) mbar_init(bars + 8 * i, 1);
                fence_barrier_init();
                fence_proxy_async_smem();
                PROFX(88);
            }
            __syncwarp();
            bar_arrive(0, 384);
            if (elect()) {
                if (main_cta) {
#pragma unroll 1
                    for (int k = 0; k < 5; k++) {
                        const uint32_t full = bars + 8 * (BAR_FULL + k), st = sb + k * SLOT;
                        mbar_expect_tx(full, SLOT);
                        tma_load_4d(st, &mapB, full, k * 64, 0, 0, dt * 8);
                        tma_load_4d(st + 16384, &mapX, full, k * 64, 0, 0, tc * 64);
                        if (k == 0) PROFX(89);
                        if (P_R0) pause(P_R0);
                    }
                }
                PROF(27);
            }
            __syncwarp();
            bar_sync(7, 64);
            if (main_cta && elect()) {
                int s = 0; uint32_t ph = 0;
#pragma unroll 1
                for (int k = 5; k < 68; k++) {
                    mbar_wait(bars + 8 * (BAR_EMPTY + s), ph);
                    const uint32_t st = sb + s * SLOT;
                    const unsigned kv = k - 32 - VPOS;
                    const uint32_t full = bars + 8 * (BAR_FULL + s + ((k >> 4) == 1 || kv < 4 ? 5 : 0));
                    mbar_expect_tx(full, SLOT);
                    if (k < 32) {
                        tma_load_4d(st + 16384, &mapX, full, (k & 15) * 64, 0, 0, tc * 64);
                        tma_load_4d(st, &mapB, full, (k & 15) * 64, 0, 0, dt * 8 + (k >> 4) * 64);
                    } else if (kv < 4) {
                        if (kv == 0) mbar_wait(bars + 8 * (BAR_F + 2), 0);
                        tma_load_3d(st, &mapV, full, 0, kv * 64, rp * 32 + dt * 2);
                        tma_load_3d(st + 16384, &mapV, full, 0, kv * 64, rp * 32 + 16 + dt * 2);
                    } else {
                        const int h = k < 32 + VPOS ? k - 32 : k - 36;
                        tma_load_3d(st + 16384, &mapCre + (h & 1), full, 0, dt * 128, h >> 1);
                        if ((h & 15) == 0) mbar_wait(bars + 8 * (BAR_F + (h >> 4)), 0);
                        bulk_load(st, g_hT + (h * 16 + tc) * 16384, 16384, full);
                    }
                    if (++s == (k < 15 ? 5 : NS)) { s = 0; ph ^= 1; }
                }
            }
        } else {
            const unsigned epoch = load_epoch();
            bar_sync(0, 384);
            if (w == 1) {
                bar_arrive(7, 64);
                if (elect()) {
                    if (main_cta) {
                        pause(T_XS);
                        bulk_load(sb + OFF_GW, P.gate_w + (b & 15) * 64, 128, bars + 8 * BAR_XC);
#pragma unroll 1
                        for (int c = 0; c < 4; c++) {
                            mbar_expect_tx(bars + 8 * (BAR_XC + c), c ? 8192 : 8192 + 128);
                            tma_load_4d(sb + OFF_U + c * 8192, &mapXs, bars + 8 * (BAR_XC + c), (b & 15) * 64, 0, c, b >> 4);
                            pause(P_XS);
                        }
                    }
                    mbar_wait(bars + 8 * BAR_S1, 0);
                    if (main_cta) {
#pragma unroll
                        for (int c = 0; c < 4; c++) {
                            if (c) pause(PACE_U);
                            tma_store_4d(&mapU0, sb + OFF_U + c * 8192, (b & 15) * 64, 32 * c, 0, b >> 4);
                        }
                        bulk_store(g_gp + b * 256, sb + OFF_GW, 1024);
                        bulk_commit();
                        bulk_wait0();
                        signal_counter(&g_cnt[CNT_U * CS]);
                    }
                    PROF(9);
                    mbar_expect_tx(bars + 8 * BAR_U, 32768);
                    wait_counter(&g_cnt[CNT_U * CS], epoch * 128);
                    PROF(11);
#pragma unroll
                    for (int i = 0; i < 8; i++) {
                        if (PACE_L && i && !(i & 1)) pause(PACE_L);
                        tma_load_4d(sb + OFF_U + i * 4096, &mapU2, bars + 8 * BAR_U, 0, 0, (i & 3) * 4, b == 128 ? 1 : b == 0 ? 0 : 2 * b + (i >> 2));
                    }
                    if (main_cta) {
#pragma unroll 1
                        for (int i = 0; i < 2; i++) {
#pragma unroll 1
                            for (int j = 0; j < 2 * HN; j++) {
                                const int hf = j / HN, jj = j % HN;
                                if (jj == 0) mbar_wait(bars + 8 * (BAR_HW + hf), i);
                                if (j) pause(i ? PACE_HB : PACE_HA);
                                tma_store_3d(&mapH, sb + OFF_HS + hf * (16384 + i * 18432) + jj * (16384 / HN), 0, 2 * tc + hf, (dt + 8 * i) * 8 + jj * (8 / HN));
                            }
                            bulk_commit();
                            bulk_wait0();
                            signal_counter(&g_cnt[(CNT_H + i) * CS]);
                            mbar_arrive(bars + 8 * (BAR_HD + i));
                            PROF(i ? 6 : 26);
                            wait_counter(&g_cnt[(CNT_H + i) * CS], epoch * 128);
                            mbar_arrive(bars + 8 * (BAR_F + i));
                            PROF(1 + i);
                        }
                    }
                }
            } else {
                const int ld = (1026 * cls) >> 7, lm = (1026 * ((256 - cls) & 255)) >> 7;
                if (elect() && main_cta) {
                    if (w == 3) {
                        pause(T_W);
#pragma unroll 1
                        for (int i = 0; i < 8; i++) {
                            tma_prefetch_4d(&mapWr + (i & 1), 0, (i & 2) ? lm : ld, i >> 2, 0);
                            pause(200);
                        }
                        bulk_prefetch_l2(c_inv + b * 128, 1024);
                    } else {
                        pause(T_BA + D_XS * tc);
                        if (tc > 4) tma_prefetch_4d(&mapB, tc * 64, 0, 0, dt * 8);
                        pause(T_B2);
                        bulk_prefetch_l2(((b & 1) ? P.b_im : P.b_re) + (64 + (b >> 1)) * 8192, 16384);
                        pause(T_W0 - D_XS * tc);
                    }
                }
#pragma unroll 1
                for (int ps = 0; ps < 2; ps++) {
                    const uint32_t wb = sb + OFF_W + (1 - ps) * 18432;
                    if (w == 2 && elect()) {
                        const uint32_t bw = bars + 8 * (BAR_W + ps);
                        if (ps && main_cta) mbar_wait(bars + 8 * BAR_HD, 0);
                        mbar_expect_tx(bw, ps ? 18432 : 18432 + 8192);
#pragma unroll 1
                        for (int i = 0; i < 4; i++) {
                            tma_load_4d(wb + (i >> 1) * 4608 + (i & 1) * 9216, &mapWr + (i & 1), bw, 0, i < 2 ? ld : lm, (i < 2 || b == 0) ? ps : 1 - ps, 0);
                            pause(P_W);
                        }
                        if (!ps) bulk_load(sb + OFF_F, c_tab + 8192, 8192, bw);
                        PROFX(85 + ps);
                    }
                    if (w == 3 && ps && main_cta && elect()) {
#pragma unroll 1
                        for (int i = 0; i < 8; i++) {
                            bulk_prefetch_l2(((b & 1) ? P.c_im : P.c_re) + (size_t)(b >> 1) * 16384 + i * 2048, 4096);
                            pause(P_C);
                        }
                    }
                    __syncwarp();
                    mbar_wait(bars + 8 * (BAR_W + ps), 0);
                    if (tid == 320) PROF(ps ? 31 : 10);
#pragma unroll 1
                    for (int u = 0; u < 4; u++) {
                        const int row = 2 * (w - 2) + (u >> 1), pl = u & 1;
                        const uint32_t dp = wb + pl * 9216 + row * 1152, mp = wb + pl * 9216 + 4608 + ((b == 0 && ps == 0) ? (4 - row) & 3 : 3 - row) * 1152;
                        const uint32_t od = dp + ((1026 * cls) & 127), om = mp + ((1026 * (256 - cls)) & 127);
                        uint32_t v[4][8], o[4][4];
#pragma unroll
                        for (int i = 0; i < 8; i++) {
                            const uint4 r = lds128u((i < 4 ? (od & ~15u) + 16 * lane + (i >> 1) * 512 : ((om + 1010) & ~15u) - 16 * lane - ((i >> 1) & 1) * 512) + (i & 1) * 16);
                            uint32_t* d = &v[i >> 1][4 * (i & 1)];
                            d[0] = r.x; d[1] = r.y; d[2] = r.z; d[3] = r.w;
                        }
                        const uint32_t e0 = lds16(om), e1 = lds16(od + 1024);
                        auto fwd = [&](int ws) {
#pragma unroll
                            for (int k = 0; k < 8; k++) o[k >> 2][k & 3] = __byte_perm(v[k >> 2][ws + (k & 3)], v[k >> 2][ws + (k & 3) + 1], (cls & 1) ? 0x5432 : 0x3210);
                        };
                        auto mir = [&](int ws) {
#pragma unroll
                            for (int k = 8; k < 16; k++) o[k >> 2][k & 3] = __byte_perm(v[k >> 2][ws + 3 - (k & 3)], v[k >> 2][ws + 4 - (k & 3)], (cls & 1) ? 0x1032 : 0x3254);
                        };
                        switch ((cls >> 1) & 3) { case 0: fwd(0); break; case 1: fwd(1); break; case 2: fwd(2); break; default: fwd(3); }
                        switch (((1 - cls) >> 1) & 3) { case 0: mir(0); break; case 1: mir(1); break; case 2: mir(2); break; default: mir(3); }
                        if (lane == 0) {
                            o[0][0] = pack2(fmaf(pl ? -0.5f : 0.5f, bf_lo(e0), 0.5f * bf_lo(o[0][0])), bf_hi(o[0][0]));
                            o[2][0] = pack2(fmaf(pl ? -0.5f : 0.5f, bf_lo(e1), 0.5f * bf_lo(o[2][0])), bf_hi(o[2][0]));
                        }
                        __syncwarp();
#pragma unroll
                        for (int i = 0; i < 4; i++)
                            sts128u((i < 2 ? dp : mp) + (i & 1) * 512 + ((lane * 16) ^ ((lane << 1) & 48)), o[i][0], o[i][1], o[i][2], o[i][3]);
                    }
                    if (ps) fence_proxy_async_smem();
                    mbar_arrive(bars + 8 * (BAR_C + ps));
                    if (tid == 320) PROF(ps ? 12 : 28);
                }
                if (elect()) {
                    if (w == 3) {
                        if (main_cta) {
                            mbar_wait(bars + 8 * (BAR_HD + 1), 0);
                            mbar_expect_tx(bars + 8 * BAR_X, 32768);
#pragma unroll 1
                            for (int i = 0; i < 4; i++) {
                                pause(P_XE);
                                tma_load_3d(sb + OFF_HS + (i & 1) * 8192 + (i >> 1) * 34816, &mapXe, bars + 8 * BAR_X, 128 * dt + 64 * (i >> 1), 64 * mq, 2 * rp + (i & 1));
                            }
                            mbar_wait(bars + 8 * BAR_U, 1);
                            mbar_expect_tx(bars + 8 * BAR_T, 32768);
#pragma unroll 1
                            for (int j = 0; j < 4; j++) {
                                bulk_load(sb + OFF_U + j * 8192, c_inv + mq * 4096 + j * 1024, 8192, bars + 8 * BAR_T);
                                pause(P_T);
                            }
                        }
                    } else {
                        mbar_wait(bars + 8 * BAR_VW, 0);
#pragma unroll 1
                        for (int i = 0; i < (real_cls ? 4 : 8); i++) {
                            if (i) pause(PACE_V);
                            tma_store_4d(&mapU2, sb + OFF_U + i * 4096, 0, 0, (i & 3) * 4, b == 128 ? 1 : 2 * b + (i >> 2));
                        }
                        bulk_commit();
                        bulk_wait_read();
                        mbar_arrive(bars + 8 * BAR_U);
                        bulk_wait0();
                        signal_counter(&g_cnt[CNT_V * CS]);
                        PROF(13);
                        if (main_cta) {
                            wait_counter(&g_cnt[CNT_V * CS], epoch * 129);
                            mbar_arrive(bars + 8 * (BAR_F + 2));
                            PROF(14);
                        }
                    }
                }
            }
        }
    }
}

typedef CUresult (*PFN_encodeTiled)(CUtensorMap*, CUtensorMapDataType, cuuint32_t, void*, const cuuint64_t*, const cuuint64_t*,
                                    const cuuint32_t*, const cuuint32_t*, CUtensorMapInterleave, CUtensorMapSwizzle,
                                    CUtensorMapL2promotion, CUtensorMapFloatOOBfill);

static CUtensorMap make_map(PFN_encodeTiled enc, const void* ptr, int rank, const cuuint64_t* dims, const cuuint64_t* strides, const cuuint32_t* box,
                            CUtensorMapSwizzle sw = CU_TENSOR_MAP_SWIZZLE_128B, CUtensorMapDataType dt = CU_TENSOR_MAP_DATA_TYPE_BFLOAT16) {
    CUtensorMap m;
    cuuint32_t es[5] = {1, 1, 1, 1, 1};
    enc(&m, dt, rank, (void*)ptr, dims, strides, box, es, CU_TENSOR_MAP_INTERLEAVE_NONE,
        sw, CU_TENSOR_MAP_L2_PROMOTION_L2_128B, CU_TENSOR_MAP_FLOAT_OOB_FILL_NONE);
    return m;
}

extern "C" void kernel_launch(void* const* d_in, const int* in_sizes, int n_in, void* d_out, int out_size) {
    const bf16* x = (const bf16*)d_in[0];
    const bf16* wr = (const bf16*)d_in[1];
    const bf16* wi = (const bf16*)d_in[2];
    const bf16* Bre = (const bf16*)d_in[6];
    const bf16* Bim = (const bf16*)d_in[7];
    const bf16* Cre = (const bf16*)d_in[8];
    const bf16* Cim = (const bf16*)d_in[9];

    void* fn = nullptr;
    cudaDriverEntryPointQueryResult st;
    cudaGetDriverEntryPoint("cuTensorMapEncodeTiled", &fn, cudaEnableDefault, &st);
    PFN_encodeTiled enc = (PFN_encodeTiled)fn;
    void *p_hT, *p_U;
    cudaGetSymbolAddress(&p_hT, g_hT);
    cudaGetSymbolAddress(&p_U, g_U);

    Params P;
    P.lam_re = (const bf16*)d_in[4]; P.lam_im = (const bf16*)d_in[5]; P.log_dt = (const bf16*)d_in[10];
    P.dskip = (const bf16*)d_in[11]; P.gate_w = (const bf16*)d_in[12]; P.c_re = Cre; P.c_im = Cim; P.b_re = Bre; P.b_im = Bim; P.x = x;
    P.swapB = Bim < Bre;

    CUtensorMap mB, mX, mCre, mCim, mXs, mU0, mV, mU2, mXe, mO, mWr, mWi, mH;
    {
        cuuint64_t d[4] = {64, 2052, 2, 4}, s[3] = {128, 262656, 525312};
        cuuint32_t bx[4] = {64, 9, 1, 4};
        mWr = make_map(enc, wr, 4, d, s, bx, CU_TENSOR_MAP_SWIZZLE_NONE);
        mWi = make_map(enc, wi, 4, d, s, bx, CU_TENSOR_MAP_SWIZZLE_NONE);
    }
    {
        cuuint64_t d[3] = {256, 32, 128}, s[2] = {2048, 65536};
        cuuint32_t bx[3] = {256, 1, 8 / HN};
        mH = make_map(enc, p_hT, 3, d, s, bx, CU_TENSOR_MAP_SWIZZLE_NONE, CU_TENSOR_MAP_DATA_TYPE_UINT64);
    }
    {
        const bf16* lo = P.swapB ? Bim : Bre; const bf16* hi = P.swapB ? Bre : Bim;
        cuuint64_t d[4] = {1024, 8, 2, 128}, s[3] = {2048, (cuuint64_t)((const char*)hi - (const char*)lo), 16384};
        cuuint32_t bx[4] = {64, 8, 2, 8};
        mB = make_map(enc, lo, 4, d, s, bx);
    }
    {
        cuuint64_t d[4] = {1024, 2, 4, 976}, s[3] = {2048, 32 * 2048, 2 * 2048};
        cuuint32_t bx[4] = {64, 2, 4, 16};
        mX = make_map(enc, x, 4, d, s, bx);
    }
    {
        cuuint64_t d[3] = {64, 1024, 16}, s[2] = {2048, 128};
        cuuint32_t bx[3] = {64, 128, 1};
        mCre = make_map(enc, Cre, 3, d, s, bx);
        mCim = make_map(enc, Cim, 3, d, s, bx);
    }
    {
        cuuint64_t d[3] = {64, 256, 128}, s[2] = {16384, 128};
        cuuint32_t bx[3] = {64, 64, 2};
        mV = make_map(enc, p_U, 3, d, s, bx);
    }
    {
        cuuint64_t d[3] = {1024, 256, 8}, s[2] = {8 * 2048, 2048};
        cuuint32_t bx[3] = {64, 64, 1};
        mXe = make_map(enc, x, 3, d, s, bx);
    }
    {
        cuuint64_t d[4] = {1024, 2, 4, 256}, s[3] = {4096, 2 * 4096, 8 * 4096};
        cuuint32_t bx[4] = {32, 2, 1, 8};
        mO = make_map(enc, d_out, 4, d, s, bx, CU_TENSOR_MAP_SWIZZLE_128B, CU_TENSOR_MAP_DATA_TYPE_FLOAT32);
    }
    {
        cuuint64_t d[4] = {1024, 64, 4, 8}, s[3] = {32 * 2048, 8 * 2048, 2048};
        cuuint32_t bx[4] = {64, 64, 1, 1};
        mXs = make_map(enc, x, 4, d, s, bx);
    }
    {
        cuuint64_t d[4] = {1024, 128, 2, 8}, s[3] = {32768, 16384, 2048};
        cuuint32_t bx[4] = {64, 32, 2, 1};
        mU0 = make_map(enc, p_U, 4, d, s, bx);
    }
    {
        cuuint64_t d[4] = {64, 8, 16, 256}, s[3] = {2048, 128, 16384};
        cuuint32_t bx[4] = {64, 8, 4, 1};
        mU2 = make_map(enc, p_U, 4, d, s, bx);
    }
    cudaFuncSetAttribute(fused_kernel, cudaFuncAttributeMaxDynamicSharedMemorySize, SMEM_BYTES);
    fused_kernel<<<130, 384, SMEM_BYTES, cudaStreamPerThread>>>(mB, mX, mXs, mU0, mU2, mXe, mCre, mCim, mV, mO, mWr, mWi, mH, P);
}
```

```cpp
#include <cuda_runtime.h>
#include <cuda_bf16.h>
#include <cuda.h>
#include <stdint.h>

typedef __nv_bfloat16 bf16;

__device__ const __align__(128) uint32_t c_tab[11264] = {
0x3f803f80,0xbf803f80,0x3f803f80,0xbf803f80,0x3f803f80,0xbf803f80,0x3f803f80,0xbf803f80,0x3f803f80,0xbf803f80,0x3f803f80,0xbf803f80,
0x3f803f80,0xbf803f80,0x3f803f80,0xbf803f80,0x3f7f3f80,0xbdc98000,0x3f223f35,0xbf46bf35,0x3f753f7b,0xbe95be48,0x3ef13f0e,0xbf62bf55,
0x3f623f6d,0xbef1bec4,0x3e953ec4,0xbf75bf6d,0x3f463f55,0xbf22bf0e,0x3dc93e48,0xbf7fbf7b,0x3f7b3f80,0xbe488000,0xbe480000,0xbf7bbf80,
0x3f553f6d,0xbf0ebec4,0xbf0ebec4,0xbf55bf6d,0x3f0e3f35,0xbf55bf35,0xbf55bf35,0xbf0ebf35,0x3e483ec4,0xbf7bbf6d,0xbf7bbf6d,0xbe48bec4,
0x3f753f80,0xbe958000,0xbf62bf35,0xbef1bf35,0x3f223f55,0xbf46bf0e,0xbf7fbf7b,0x3dc9be48,0x3dc93ec4,0xbf7fbf6d,0xbf46bf6d,0x3f223ec4,
0xbef1be48,0xbf62bf7b,0xbe95bf0e,0x3f753f55,0x3f6d3f80,0xbec48000,0xbf6dbf80,0x3ec48000,0x3ec43f35,0xbf6dbf35,0xbec4bf35,0x3f6d3f35,
0xbec40000,0xbf6dbf80,0x3ec40000,0x3f6d3f80,0xbf6dbf35,0xbec4bf35,0x3f6d3f35,0x3ec43f35,0x3f623f80,0xbef18000,0xbe95bf35,0x3f753f35,
0x3dc93f0e,0xbf7fbf55,0x3f223e48,0x3f463f7b,0xbf46bec4,0xbf22bf6d,0x3f7f3f6d,0xbdc93ec4,0xbf75bf7b,0x3e95be48,0x3ef13f55,0xbf62bf0e,
0x3f553f80,0xbf0e8000,0x3f0e0000,0x3f553f80,0xbe483ec4,0xbf7bbf6d,0x3f7b3f6d,0xbe483ec4,0xbf7bbf35,0xbe48bf35,0x3e483f35,0xbf7bbf35,
0xbf0ebf6d,0x3f553ec4,0xbf55bec4,0xbf0ebf6d,0x3f463f80,0xbf228000,0x3f7f3f35,0x3dc93f35,0xbef13e48,0xbf62bf7b,0x3e953f55,0xbf75bf0e,
0xbf75bf6d,0x3e95bec4,0xbf62bec4,0xbef1bf6d,0x3dc9bf0e,0x3f7f3f55,0xbf22bf7b,0x3f463e48,0x3f353f80,0xbf358000,0x3f353f80,0xbf358000,
0xbf350000,0xbf35bf80,0xbf350000,0xbf35bf80,0xbf35bf80,0x3f358000,0xbf35bf80,0x3f358000,0x3f350000,0x3f353f80,0x3f350000,0x3f353f80,
0x3f223f80,0xbf468000,0xbdc93f35,0xbf7fbf35,0xbf62be48,0xbef1bf7b,0xbf75bf55,0x3e95bf0e,0xbe95bf6d,0x3f753ec4,0x3ef1bec4,0x3f623f6d,
0x3f7f3f0e,0x3dc93f55,0x3f463f7b,0xbf223e48,0x3f0e3f80,0xbf558000,0xbf550000,0xbf0ebf80,0xbf7bbec4,0xbe48bf6d,0xbe48bf6d,0x3f7b3ec4,
0x3e48bf35,0x3f7b3f35,0x3f7b3f35,0xbe483f35,0x3f553f6d,0xbf0e3ec4,0xbf0e3ec4,0xbf55bf6d,0x3ef13f80,0xbf628000,0xbf75bf35,0x3e95bf35,
0xbf7fbf0e,0x3dc9bf55,0x3f46be48,0x3f223f7b,0x3f22bec4,0x3f463f6d,0x3dc93f6d,0xbf7fbec4,0x3e953f7b,0xbf75be48,0xbf62bf55,0x3ef1bf0e,
0x3ec43f80,0xbf6d8000,0xbec4bf80,0x3f6d8000,0xbf6dbf35,0x3ec4bf35,0x3f6d3f35,0xbec43f35,0x3f6d0000,0x3ec43f80,0xbf6d0000,0xbec4bf80,
0xbec43f35,0xbf6dbf35,0x3ec4bf35,0x3f6d3f35,0x3e953f80,0xbf758000,0x3ef1bf35,0x3f623f35,0xbf46bf55,0x3f22bf0e,0x3dc93f7b,0xbf7fbe48,
0x3f7f3ec4,0xbdc93f6d,0xbf22bf6d,0x3f46bec4,0xbf623e48,0xbef1bf7b,0x3f753f0e,0xbe953f55,0x3e483f80,0xbf7b8000,0x3f7b0000,0x3e483f80,
0xbf0ebf6d,0x3f55bec4,0xbf553ec4,0xbf0ebf6d,0x3f553f35,0xbf0e3f35,0x3f0ebf35,0x3f553f35,0xbf7bbec4,0x3e48bf6d,0xbe483f6d,0xbf7bbec4,
0x3dc93f80,0xbf7f8000,0x3f463f35,0xbf223f35,0xbe95bf7b,0x3f75be48,0xbf62bf0e,0x3ef1bf55,0x3ef13f6d,0xbf623ec4,0x3f753ec4,0xbe953f6d,
0xbf22bf55,0x3f46bf0e,0xbf7fbe48,0x3dc9bf7b,0x3f80,0xbf808000,0x3f80,0xbf808000,0xbf80,0x3f808000,0xbf80,0x3f808000,
0x3f80,0xbf808000,0x3f80,0xbf808000,0xbf80,0x3f808000,0xbf80,0x3f808000,0xbdc93f80,0xbf7f8000,0xbf463f35,0xbf22bf35,
0x3e95bf7b,0x3f753e48,0x3f62bf0e,0x3ef13f55,0xbef13f6d,0xbf62bec4,0xbf753ec4,0xbe95bf6d,0x3f22bf55,0x3f463f0e,0x3f7fbe48,0x3dc93f7b,
0xbe483f80,0xbf7b8000,0xbf7b0000,0x3e48bf80,0x3f0ebf6d,0x3f553ec4,0x3f553ec4,0xbf0e3f6d,0xbf553f35,0xbf0ebf35,0xbf0ebf35,0x3f55bf35,
0x3f7bbec4,0x3e483f6d,0x3e483f6d,0xbf7b3ec4,0xbe953f80,0xbf758000,0xbef1bf35,0x3f62bf35,0x3f46bf55,0x3f223f0e,0xbdc93f7b,0xbf7f3e48,
0xbf7f3ec4,0xbdc9bf6d,0x3f22bf6d,0x3f463ec4,0x3f623e48,0xbef13f7b,0xbf753f0e,0xbe95bf55,0xbec43f80,0xbf6d8000,0x3ec4bf80,0x3f6d8000,
0x3f6dbf35,0x3ec43f35,0xbf6d3f35,0xbec4bf35,0xbf6d0000,0x3ec4bf80,0x3f6d0000,0xbec43f80,0x3ec43f35,0xbf6d3f35,0xbec4bf35,0x3f6dbf35,
0xbef13f80,0xbf628000,0x3f75bf35,0x3e953f35,0x3f7fbf0e,0x3dc93f55,0xbf46be48,0x3f22bf7b,0xbf22bec4,0x3f46bf6d,0xbdc93f6d,0xbf7f3ec4,
0xbe953f7b,0xbf753e48,0x3f62bf55,0x3ef13f0e,0xbf0e3f80,0xbf558000,0x3f550000,0xbf0e3f80,0x3f7bbec4,0xbe483f6d,0x3e48bf6d,0x3f7bbec4,
0xbe48bf35,0x3f7bbf35,0xbf7b3f35,0xbe48bf35,0xbf553f6d,0xbf0ebec4,0x3f0e3ec4,0xbf553f6d,0xbf223f80,0xbf468000,0x3dc93f35,0xbf7f3f35,
0x3f62be48,0xbef13f7b,0x3f75bf55,0x3e953f0e,0x3e95bf6d,0x3f75bec4,0xbef1bec4,0x3f62bf6d,0xbf7f3f0e,0x3dc9bf55,0xbf463f7b,0xbf22be48,
0xbf353f80,0xbf358000,0xbf353f80,0xbf358000,0x3f350000,0xbf353f80,0x3f350000,0xbf353f80,0x3f35bf80,0x3f358000,0x3f35bf80,0x3f358000,
0xbf350000,0x3f35bf80,0xbf350000,0x3f35bf80,0xbf463f80,0xbf228000,0xbf7f3f35,0x3dc9bf35,0x3ef13e48,0xbf623f7b,0xbe953f55,0xbf753f0e,
0x3f75bf6d,0x3e953ec4,0x3f62bec4,0xbef13f6d,0xbdc9bf0e,0x3f7fbf55,0x3f22bf7b,0x3f46be48,0xbf553f80,0xbf0e8000,0xbf0e0000,0x3f55bf80,
0x3e483ec4,0xbf7b3f6d,0xbf7b3f6d,0xbe48bec4,0x3f7bbf35,0xbe483f35,0xbe483f35,0xbf7b3f35,0x3f0ebf6d,0x3f55bec4,0x3f55bec4,0xbf0e3f6d,
0xbf623f80,0xbef18000,0x3e95bf35,0x3f75bf35,0xbdc93f0e,0xbf7f3f55,0xbf223e48,0x3f46bf7b,0x3f46bec4,0xbf223f6d,0xbf7f3f6d,0xbdc9bec4,
0x3f75bf7b,0x3e953e48,0xbef13f55,0xbf623f0e,0xbf6d3f80,0xbec48000,0x3f6dbf80,0x3ec48000,0xbec43f35,0xbf6d3f35,0x3ec4bf35,0x3f6dbf35,
0x3ec40000,0xbf6d3f80,0xbec40000,0x3f6dbf80,0x3f6dbf35,0xbec43f35,0xbf6d3f35,0x3ec4bf35,0xbf753f80,0xbe958000,0x3f62bf35,0xbef13f35,
0xbf223f55,0xbf463f0e,0x3f7fbf7b,0x3dc93e48,0xbdc93ec4,0xbf7f3f6d,0x3f46bf6d,0x3f22bec4,0x3ef1be48,0xbf623f7b,0x3e95bf0e,0x3f75bf55,
0xbf7b3f80,0xbe488000,0x3e480000,0xbf7b3f80,0xbf553f6d,0xbf0e3ec4,0x3f0ebec4,0xbf553f6d,0xbf0e3f35,0xbf553f35,0x3f55bf35,0xbf0e3f35,
0xbe483ec4,0xbf7b3f6d,0x3f7bbf6d,0xbe483ec4,0xbf7f3f80,0xbdc98000,0xbf223f35,0xbf463f35,0xbf753f7b,0xbe953e48,0xbef13f0e,0xbf623f55,
0xbf623f6d,0xbef13ec4,0xbe953ec4,0xbf753f6d,0xbf463f55,0xbf223f0e,0xbdc93e48,0xbf7f3f7b,0x3f803f80,0xbf803f80,0x3f803f80,0xbf803f80,
0x3f803f80,0xbf803f80,0x3f803f80,0xbf803f80,0x3f803f80,0xbf803f80,0x3f803f80,0xbf803f80,0x3f803f80,0xbf803f80,0x3f803f80,0xbf803f80,
0xbdc90000,0xbf7fbf80,0xbf46bf35,0xbf22bf35,0xbe95be48,0xbf75bf7b,0xbf62bf55,0xbef1bf0e,0xbef1bec4,0xbf62bf6d,0xbf75bf6d,0xbe95bec4,
0xbf22bf0e,0xbf46bf55,0xbf7fbf7b,0xbdc9be48,0xbf7bbf80,0x3e488000,0x3e480000,0x3f7b3f80,0xbf55bf6d,0x3f0e3ec4,0x3f0e3ec4,0x3f553f6d,
0xbf0ebf35,0x3f553f35,0x3f553f35,0x3f0e3f35,0xbe48bec4,0x3f7b3f6d,0x3f7b3f6d,0x3e483ec4,0x3e950000,0x3f753f80,0x3ef13f35,0xbf62bf35,
0x3f463f0e,0x3f223f55,0xbdc93e48,0xbf7fbf7b,0x3f7f3f6d,0x3dc93ec4,0xbf22bec4,0xbf46bf6d,0x3f623f7b,0xbef1be48,0xbf75bf55,0xbe95bf0e,
0x3f6d3f80,0xbec48000,0xbf6dbf80,0x3ec48000,0x3ec43f35,0xbf6dbf35,0xbec4bf35,0x3f6d3f35,0xbec40000,0xbf6dbf80,0x3ec40000,0x3f6d3f80,
0xbf6dbf35,0xbec4bf35,0x3f6d3f35,0x3ec43f35,0xbef10000,0xbf62bf80,0x3f753f35,0x3e953f35,0xbf7fbf55,0xbdc9bf0e,0x3f463f7b,0xbf22be48,
0xbf22bf6d,0x3f463ec4,0xbdc93ec4,0xbf7fbf6d,0x3e95be48,0x3f753f7b,0xbf62bf0e,0xbef1bf55,0xbf55bf80,0x3f0e8000,0xbf0e0000,0xbf55bf80,
0x3e48bec4,0x3f7b3f6d,0xbf7bbf6d,0x3e48bec4,0x3f7b3f35,0x3e483f35,0xbe48bf35,0x3f7b3f35,0x3f0e3f6d,0xbf55bec4,0x3f553ec4,0x3f0e3f6d,
0x3f220000,0x3f463f80,0xbdc9bf35,0x3f7f3f35,0x3f623f7b,0xbef13e48,0x3f753f0e,0x3e953f55,0xbe953ec4,0xbf75bf6d,0x3ef13f6d,0xbf62bec4,
0xbf7fbf55,0x3dc9bf0e,0xbf46be48,0xbf22bf7b,0x3f353f80,0xbf358000,0x3f353f80,0xbf358000,0xbf350000,0xbf35bf80,0xbf350000,0xbf35bf80,
0xbf35bf80,0x3f358000,0xbf35bf80,0x3f358000,0x3f350000,0x3f353f80,0x3f350000,0x3f353f80,0xbf460000,0xbf22bf80,0xbf7fbf35,0x3dc9bf35,
0xbef1bf7b,0x3f623e48,0x3e95bf0e,0x3f753f55,0x3f753ec4,0x3e953f6d,0x3f623f6d,0xbef13ec4,0x3dc93f55,0xbf7fbf0e,0xbf223e48,0xbf46bf7b,
0xbf0ebf80,0x3f558000,0x3f550000,0x3f0e3f80,0x3f7b3ec4,0x3e483f6d,0x3e483f6d,0xbf7bbec4,0xbe483f35,0xbf7bbf35,0xbf7bbf35,0x3e48bf35,
0xbf55bf6d,0x3f0ebec4,0x3f0ebec4,0x3f553f6d,0x3f620000,0x3ef13f80,0xbe953f35,0xbf75bf35,0xbdc93f55,0xbf7fbf0e,0xbf22bf7b,0x3f46be48,
0xbf46bf6d,0x3f22bec4,0x3f7f3ec4,0x3dc93f6d,0x3f753e48,0x3e953f7b,0xbef13f0e,0xbf62bf55,0x3ec43f80,0xbf6d8000,0xbec4bf80,0x3f6d8000,
0xbf6dbf35,0x3ec4bf35,0x3f6d3f35,0xbec43f35,0x3f6d0000,0x3ec43f80,0xbf6d0000,0xbec4bf80,0xbec43f35,0xbf6dbf35,0x3ec4bf35,0x3f6d3f35,
0xbf750000,0xbe95bf80,0x3f623f35,0xbef13f35,0x3f22bf0e,0x3f463f55,0xbf7fbe48,0xbdc9bf7b,0xbdc93f6d,0xbf7fbec4,0x3f46bec4,0x3f223f6d,
0xbef1bf7b,0x3f62be48,0xbe953f55,0xbf75bf0e,0xbe48bf80,0x3f7b8000,0xbf7b0000,0xbe48bf80,0x3f0e3f6d,0xbf553ec4,0x3f55bec4,0x3f0e3f6d,
0xbf55bf35,0x3f0ebf35,0xbf0e3f35,0xbf55bf35,0x3f7b3ec4,0xbe483f6d,0x3e48bf6d,0x3f7b3ec4,0x3f7f0000,0x3dc93f80,0x3f22bf35,0x3f463f35,
0xbf753e48,0xbe95bf7b,0xbef13f55,0xbf62bf0e,0x3f62bec4,0x3ef13f6d,0x3e95bf6d,0x3f753ec4,0xbf463f0e,0xbf22bf55,0xbdc93f7b,0xbf7fbe48,
0x3f80,0xbf808000,0x3f80,0xbf808000,0xbf80,0x3f808000,0xbf80,0x3f808000,0x3f80,0xbf808000,0x3f80,0xbf808000,
0xbf80,0x3f808000,0xbf80,0x3f808000,0xbf7f0000,0x3dc9bf80,0xbf22bf35,0x3f46bf35,0x3f753e48,0xbe953f7b,0x3ef13f55,0xbf623f0e,
0xbf62bec4,0x3ef1bf6d,0xbe95bf6d,0x3f75bec4,0x3f463f0e,0xbf223f55,0x3dc93f7b,0xbf7f3e48,0x3e48bf80,0x3f7b8000,0x3f7b0000,0xbe483f80,
0xbf0e3f6d,0xbf55bec4,0xbf55bec4,0x3f0ebf6d,0x3f55bf35,0x3f0e3f35,0x3f0e3f35,0xbf553f35,0xbf7b3ec4,0xbe48bf6d,0xbe48bf6d,0x3f7bbec4,
0x3f750000,0xbe953f80,0xbf623f35,0xbef1bf35,0xbf22bf0e,0x3f46bf55,0x3f7fbe48,0xbdc93f7b,0x3dc93f6d,0xbf7f3ec4,0xbf46bec4,0x3f22bf6d,
0x3ef1bf7b,0x3f623e48,0x3e953f55,0xbf753f0e,0xbec43f80,0xbf6d8000,0x3ec4bf80,0x3f6d8000,0x3f6dbf35,0x3ec43f35,0xbf6d3f35,0xbec4bf35,
0xbf6d0000,0x3ec4bf80,0x3f6d0000,0xbec43f80,0x3ec43f35,0xbf6d3f35,0xbec4bf35,0x3f6dbf35,0xbf620000,0x3ef1bf80,0x3e953f35,0xbf753f35,
0x3dc93f55,0xbf7f3f0e,0x3f22bf7b,0x3f463e48,0x3f46bf6d,0x3f223ec4,0xbf7f3ec4,0x3dc9bf6d,0xbf753e48,0x3e95bf7b,0x3ef13f0e,0xbf623f55,
0x3f0ebf80,0x3f558000,0xbf550000,0x3f0ebf80,0xbf7b3ec4,0x3e48bf6d,0xbe483f6d,0xbf7b3ec4,0x3e483f35,0xbf7b3f35,0x3f7bbf35,0x3e483f35,
0x3f55bf6d,0x3f0e3ec4,0xbf0ebec4,0x3f55bf6d,0x3f460000,0xbf223f80,0x3f7fbf35,0x3dc93f35,0x3ef1bf7b,0x3f62be48,0xbe95bf0e,0x3f75bf55,
0xbf753ec4,0x3e95bf6d,0xbf623f6d,0xbef1bec4,0xbdc93f55,0xbf7f3f0e,0x3f223e48,0xbf463f7b,0xbf353f80,0xbf358000,0xbf353f80,0xbf358000,
0x3f350000,0xbf353f80,0x3f350000,0xbf353f80,0x3f35bf80,0x3f358000,0x3f35bf80,0x3f358000,0xbf350000,0x3f35bf80,0xbf350000,0x3f35bf80,
0xbf220000,0x3f46bf80,0x3dc9bf35,0x3f7fbf35,0xbf623f7b,0xbef1be48,0xbf753f0e,0x3e95bf55,0x3e953ec4,0xbf753f6d,0xbef13f6d,0xbf623ec4,
0x3f7fbf55,0x3dc93f0e,0x3f46be48,0xbf223f7b,0x3f55bf80,0x3f0e8000,0x3f0e0000,0xbf553f80,0xbe48bec4,0x3f7bbf6d,0x3f7bbf6d,0x3e483ec4,
0xbf7b3f35,0x3e48bf35,0x3e48bf35,0x3f7bbf35,0xbf0e3f6d,0xbf553ec4,0xbf553ec4,0x3f0ebf6d,0x3ef10000,0xbf623f80,0xbf753f35,0x3e95bf35,
0x3f7fbf55,0xbdc93f0e,0xbf463f7b,0xbf223e48,0x3f22bf6d,0x3f46bec4,0x3dc93ec4,0xbf7f3f6d,0xbe95be48,0x3f75bf7b,0x3f62bf0e,0xbef13f55,
0xbf6d3f80,0xbec48000,0x3f6dbf80,0x3ec48000,0xbec43f35,0xbf6d3f35,0x3ec4bf35,0x3f6dbf35,0x3ec40000,0xbf6d3f80,0xbec40000,0x3f6dbf80,
0x3f6dbf35,0xbec43f35,0xbf6d3f35,0x3ec4bf35,0xbe950000,0x3f75bf80,0xbef13f35,0xbf623f35,0xbf463f0e,0x3f22bf55,0x3dc93e48,0xbf7f3f7b,
0xbf7f3f6d,0x3dc9bec4,0x3f22bec4,0xbf463f6d,0xbf623f7b,0xbef13e48,0x3f75bf55,0xbe953f0e,0x3f7bbf80,0x3e488000,0xbe480000,0x3f7bbf80,
0x3f55bf6d,0x3f0ebec4,0xbf0e3ec4,0x3f55bf6d,0x3f0ebf35,0x3f55bf35,0xbf553f35,0x3f0ebf35,0x3e48bec4,0x3f7bbf6d,0xbf7b3f6d,0x3e48bec4,
0x3dc90000,0xbf7f3f80,0x3f46bf35,0xbf223f35,0x3e95be48,0xbf753f7b,0x3f62bf55,0xbef13f0e,0x3ef1bec4,0xbf623f6d,0x3f75bf6d,0xbe953ec4,
0x3f22bf0e,0xbf463f55,0x3f7fbf7b,0xbdc93e48,0x3f803f80,0xbf803f80,0x3f803f80,0xbf803f80,0x3f803f80,0xbf803f80,0x3f803f80,0xbf803f80,
0x3f803f80,0xbf803f80,0x3f803f80,0xbf803f80,0x3f803f80,0xbf803f80,0x3f803f80,0xbf803f80,0xbf7fbf80,0x3dc98000,0xbf22bf35,0x3f463f35,
0xbf75bf7b,0x3e953e48,0xbef1bf0e,0x3f623f55,0xbf62bf6d,0x3ef13ec4,0xbe95bec4,0x3f753f6d,0xbf46bf55,0x3f223f0e,0xbdc9be48,0x3f7f3f7b,
0x3f7b3f80,0xbe488000,0xbe480000,0xbf7bbf80,0x3f553f6d,0xbf0ebec4,0xbf0ebec4,0xbf55bf6d,0x3f0e3f35,0xbf55bf35,0xbf55bf35,0xbf0ebf35,
0x3e483ec4,0xbf7bbf6d,0xbf7bbf6d,0xbe48bec4,0xbf75bf80,0x3e958000,0x3f623f35,0x3ef13f35,0xbf22bf55,0x3f463f0e,0x3f7f3f7b,0xbdc93e48,
0xbdc9bec4,0x3f7f3f6d,0x3f463f6d,0xbf22bec4,0x3ef13e48,0x3f623f7b,0x3e953f0e,0xbf75bf55,0x3f6d3f80,0xbec48000,0xbf6dbf80,0x3ec48000,
0x3ec43f35,0xbf6dbf35,0xbec4bf35,0x3f6d3f35,0xbec40000,0xbf6dbf80,0x3ec40000,0x3f6d3f80,0xbf6dbf35,0xbec4bf35,0x3f6d3f35,0x3ec43f35,
0xbf62bf80,0x3ef18000,0x3e953f35,0xbf75bf35,0xbdc9bf0e,0x3f7f3f55,0xbf22be48,0xbf46bf7b,0x3f463ec4,0x3f223f6d,0xbf7fbf6d,0x3dc9bec4,
0x3f753f7b,0xbe953e48,0xbef1bf55,0x3f623f0e,0x3f553f80,0xbf0e8000,0x3f0e0000,0x3f553f80,0xbe483ec4,0xbf7bbf6d,0x3f7b3f6d,0xbe483ec4,
0xbf7bbf35,0xbe48bf35,0x3e483f35,0xbf7bbf35,0xbf0ebf6d,0x3f553ec4,0xbf55bec4,0xbf0ebf6d,0xbf46bf80,0x3f228000,0xbf7fbf35,0xbdc9bf35,
0x3ef1be48,0x3f623f7b,0xbe95bf55,0x3f753f0e,0x3f753f6d,0xbe953ec4,0x3f623ec4,0x3ef13f6d,0xbdc93f0e,0xbf7fbf55,0x3f223f7b,0xbf46be48,
0x3f353f80,0xbf358000,0x3f353f80,0xbf358000,0xbf350000,0xbf35bf80,0xbf350000,0xbf35bf80,0xbf35bf80,0x3f358000,0xbf35bf80,0x3f358000,
0x3f350000,0x3f353f80,0x3f350000,0x3f353f80,0xbf22bf80,0x3f468000,0x3dc9bf35,0x3f7f3f35,0x3f623e48,0x3ef13f7b,0x3f753f55,0xbe953f0e,
0x3e953f6d,0xbf75bec4,0xbef13ec4,0xbf62bf6d,0xbf7fbf0e,0xbdc9bf55,0xbf46bf7b,0x3f22be48,0x3f0e3f80,0xbf558000,0xbf550000,0xbf0ebf80,
0xbf7bbec4,0xbe48bf6d,0xbe48bf6d,0x3f7b3ec4,0x3e48bf35,0x3f7b3f35,0x3f7b3f35,0xbe483f35,0x3f553f6d,0xbf0e3ec4,0xbf0e3ec4,0xbf55bf6d,
0xbef1bf80,0x3f628000,0x3f753f35,0xbe953f35,0x3f7f3f0e,0xbdc93f55,0xbf463e48,0xbf22bf7b,0xbf223ec4,0xbf46bf6d,0xbdc9bf6d,0x3f7f3ec4,
0xbe95bf7b,0x3f753e48,0x3f623f55,0xbef13f0e,0x3ec43f80,0xbf6d8000,0xbec4bf80,0x3f6d8000,0xbf6dbf35,0x3ec4bf35,0x3f6d3f35,0xbec43f35,
0x3f6d0000,0x3ec43f80,0xbf6d0000,0xbec4bf80,0xbec43f35,0xbf6dbf35,0x3ec4bf35,0x3f6d3f35,0xbe95bf80,0x3f758000,0xbef13f35,0xbf62bf35,
0x3f463f55,0xbf223f0e,0xbdc9bf7b,0x3f7f3e48,0xbf7fbec4,0x3dc9bf6d,0x3f223f6d,0xbf463ec4,0x3f62be48,0x3ef13f7b,0xbf75bf0e,0x3e95bf55,
0x3e483f80,0xbf7b8000,0x3f7b0000,0x3e483f80,0xbf0ebf6d,0x3f55bec4,0xbf553ec4,0xbf0ebf6d,0x3f553f35,0xbf0e3f35,0x3f0ebf35,0x3f553f35,
0xbf7bbec4,0x3e48bf6d,0xbe483f6d,0xbf7bbec4,0xbdc9bf80,0x3f7f8000,0xbf46bf35,0x3f22bf35,0x3e953f7b,0xbf753e48,0x3f623f0e,0xbef13f55,
0xbef1bf6d,0x3f62bec4,0xbf75bec4,0x3e95bf6d,0x3f223f55,0xbf463f0e,0x3f7f3e48,0xbdc93f7b,0x3f80,0xbf808000,0x3f80,0xbf808000,
0xbf80,0x3f808000,0xbf80,0x3f808000,0x3f80,0xbf808000,0x3f80,0xbf808000,0xbf80,0x3f808000,0xbf80,0x3f808000,
0x3dc9bf80,0x3f7f8000,0x3f46bf35,0x3f223f35,0xbe953f7b,0xbf75be48,0xbf623f0e,0xbef1bf55,0x3ef1bf6d,0x3f623ec4,0x3f75bec4,0x3e953f6d,
0xbf223f55,0xbf46bf0e,0xbf7f3e48,0xbdc9bf7b,0xbe483f80,0xbf7b8000,0xbf7b0000,0x3e48bf80,0x3f0ebf6d,0x3f553ec4,0x3f553ec4,0xbf0e3f6d,
0xbf553f35,0xbf0ebf35,0xbf0ebf35,0x3f55bf35,0x3f7bbec4,0x3e483f6d,0x3e483f6d,0xbf7b3ec4,0x3e95bf80,0x3f758000,0x3ef13f35,0xbf623f35,
0xbf463f55,0xbf22bf0e,0x3dc9bf7b,0x3f7fbe48,0x3f7fbec4,0x3dc93f6d,0xbf223f6d,0xbf46bec4,0xbf62be48,0x3ef1bf7b,0x3f75bf0e,0x3e953f55,
0xbec43f80,0xbf6d8000,0x3ec4bf80,0x3f6d8000,0x3f6dbf35,0x3ec43f35,0xbf6d3f35,0xbec4bf35,0xbf6d0000,0x3ec4bf80,0x3f6d0000,0xbec43f80,
0x3ec43f35,0xbf6d3f35,0xbec4bf35,0x3f6dbf35,0x3ef1bf80,0x3f628000,0xbf753f35,0xbe95bf35,0xbf7f3f0e,0xbdc9bf55,0x3f463e48,0xbf223f7b,
0x3f223ec4,0xbf463f6d,0x3dc9bf6d,0x3f7fbec4,0x3e95bf7b,0x3f75be48,0xbf623f55,0xbef1bf0e,0xbf0e3f80,0xbf558000,0x3f550000,0xbf0e3f80,
0x3f7bbec4,0xbe483f6d,0x3e48bf6d,0x3f7bbec4,0xbe48bf35,0x3f7bbf35,0xbf7b3f35,0xbe48bf35,0xbf553f6d,0xbf0ebec4,0x3f0e3ec4,0xbf553f6d,
0x3f22bf80,0x3f468000,0xbdc9bf35,0x3f7fbf35,0xbf623e48,0x3ef1bf7b,0xbf753f55,0xbe95bf0e,0xbe953f6d,0xbf753ec4,0x3ef13ec4,0xbf623f6d,
0x3f7fbf0e,0xbdc93f55,0x3f46bf7b,0x3f223e48,0xbf353f80,0xbf358000,0xbf353f80,0xbf358000,0x3f350000,0xbf353f80,0x3f350000,0xbf353f80,
0x3f35bf80,0x3f358000,0x3f35bf80,0x3f358000,0xbf350000,0x3f35bf80,0xbf350000,0x3f35bf80,0x3f46bf80,0x3f228000,0x3f7fbf35,0xbdc93f35,
0xbef1be48,0x3f62bf7b,0x3e95bf55,0x3f75bf0e,0xbf753f6d,0xbe95bec4,0xbf623ec4,0x3ef1bf6d,0x3dc93f0e,0xbf7f3f55,0xbf223f7b,0xbf463e48,
0xbf553f80,0xbf0e8000,0xbf0e0000,0x3f55bf80,0x3e483ec4,0xbf7b3f6d,0xbf7b3f6d,0xbe48bec4,0x3f7bbf35,0xbe483f35,0xbe483f35,0xbf7b3f35,
0x3f0ebf6d,0x3f55bec4,0x3f55bec4,0xbf0e3f6d,0x3f62bf80,0x3ef18000,0xbe953f35,0xbf753f35,0x3dc9bf0e,0x3f7fbf55,0x3f22be48,0xbf463f7b,
0xbf463ec4,0x3f22bf6d,0x3f7fbf6d,0x3dc93ec4,0xbf753f7b,0xbe95be48,0x3ef1bf55,0x3f62bf0e,0xbf6d3f80,0xbec48000,0x3f6dbf80,0x3ec48000,
0xbec43f35,0xbf6d3f35,0x3ec4bf35,0x3f6dbf35,0x3ec40000,0xbf6d3f80,0xbec40000,0x3f6dbf80,0x3f6dbf35,0xbec43f35,0xbf6d3f35,0x3ec4bf35,
0x3f75bf80,0x3e958000,0xbf623f35,0x3ef1bf35,0x3f22bf55,0x3f46bf0e,0xbf7f3f7b,0xbdc9be48,0x3dc9bec4,0x3f7fbf6d,0xbf463f6d,0xbf223ec4,
0xbef13e48,0x3f62bf7b,0xbe953f0e,0xbf753f55,0xbf7b3f80,0xbe488000,0x3e480000,0xbf7b3f80,0xbf553f6d,0xbf0e3ec4,0x3f0ebec4,0xbf553f6d,
0xbf0e3f35,0xbf553f35,0x3f55bf35,0xbf0e3f35,0xbe483ec4,0xbf7b3f6d,0x3f7bbf6d,0xbe483ec4,0x3f7fbf80,0x3dc98000,0x3f22bf35,0x3f46bf35,
0x3f75bf7b,0x3e95be48,0x3ef1bf0e,0x3f62bf55,0x3f62bf6d,0x3ef1bec4,0x3e95bec4,0x3f75bf6d,0x3f46bf55,0x3f22bf0e,0x3dc9be48,0x3f7fbf7b,
0x3f803f80,0xbf803f80,0x3f803f80,0xbf803f80,0x3f803f80,0xbf803f80,0x3f803f80,0xbf803f80,0x3f803f80,0xbf803f80,0x3f803f80,0xbf803f80,
0x3f803f80,0xbf803f80,0x3f803f80,0xbf803f80,0x3dc90000,0x3f7f3f80,0x3f463f35,0x3f223f35,0x3e953e48,0x3f753f7b,0x3f623f55,0x3ef13f0e,
0x3ef13ec4,0x3f623f6d,0x3f753f6d,0x3e953ec4,0x3f223f0e,0x3f463f55,0x3f7f3f7b,0x3dc93e48,0xbf7bbf80,0x3e488000,0x3e480000,0x3f7b3f80,
0xbf55bf6d,0x3f0e3ec4,0x3f0e3ec4,0x3f553f6d,0xbf0ebf35,0x3f553f35,0x3f553f35,0x3f0e3f35,0xbe48bec4,0x3f7b3f6d,0x3f7b3f6d,0x3e483ec4,
0xbe950000,0xbf75bf80,0xbef1bf35,0x3f623f35,0xbf46bf0e,0xbf22bf55,0x3dc9be48,0x3f7f3f7b,0xbf7fbf6d,0xbdc9bec4,0x3f223ec4,0x3f463f6d,
0xbf62bf7b,0x3ef13e48,0x3f753f55,0x3e953f0e,0x3f6d3f80,0xbec48000,0xbf6dbf80,0x3ec48000,0x3ec43f35,0xbf6dbf35,0xbec4bf35,0x3f6d3f35,
0xbec40000,0xbf6dbf80,0x3ec40000,0x3f6d3f80,0xbf6dbf35,0xbec4bf35,0x3f6d3f35,0x3ec43f35,0x3ef10000,0x3f623f80,0xbf75bf35,0xbe95bf35,
0x3f7f3f55,0x3dc93f0e,0xbf46bf7b,0x3f223e48,0x3f223f6d,0xbf46bec4,0x3dc9bec4,0x3f7f3f6d,0xbe953e48,0xbf75bf7b,0x3f623f0e,0x3ef13f55,
0xbf55bf80,0x3f0e8000,0xbf0e0000,0xbf55bf80,0x3e48bec4,0x3f7b3f6d,0xbf7bbf6d,0x3e48bec4,0x3f7b3f35,0x3e483f35,0xbe48bf35,0x3f7b3f35,
0x3f0e3f6d,0xbf55bec4,0x3f553ec4,0x3f0e3f6d,0xbf220000,0xbf46bf80,0x3dc93f35,0xbf7fbf35,0xbf62bf7b,0x3ef1be48,0xbf75bf0e,0xbe95bf55,
0x3e95bec4,0x3f753f6d,0xbef1bf6d,0x3f623ec4,0x3f7f3f55,0xbdc93f0e,0x3f463e48,0x3f223f7b,0x3f353f80,0xbf358000,0x3f353f80,0xbf358000,
0xbf350000,0xbf35bf80,0xbf350000,0xbf35bf80,0xbf35bf80,0x3f358000,0xbf35bf80,0x3f358000,0x3f350000,0x3f353f80,0x3f350000,0x3f353f80,
0x3f460000,0x3f223f80,0x3f7f3f35,0xbdc93f35,0x3ef13f7b,0xbf62be48,0xbe953f0e,0xbf75bf55,0xbf75bec4,0xbe95bf6d,0xbf62bf6d,0x3ef1bec4,
0xbdc9bf55,0x3f7f3f0e,0x3f22be48,0x3f463f7b,0xbf0ebf80,0x3f558000,0x3f550000,0x3f0e3f80,0x3f7b3ec4,0x3e483f6d,0x3e483f6d,0xbf7bbec4,
0xbe483f35,0xbf7bbf35,0xbf7bbf35,0x3e48bf35,0xbf55bf6d,0x3f0ebec4,0x3f0ebec4,0x3f553f6d,0xbf620000,0xbef1bf80,0x3e95bf35,0x3f753f35,
0x3dc9bf55,0x3f7f3f0e,0x3f223f7b,0xbf463e48,0x3f463f6d,0xbf223ec4,0xbf7fbec4,0xbdc9bf6d,0xbf75be48,0xbe95bf7b,0x3ef1bf0e,0x3f623f55,
0x3ec43f80,0xbf6d8000,0xbec4bf80,0x3f6d8000,0xbf6dbf35,0x3ec4bf35,0x3f6d3f35,0xbec43f35,0x3f6d0000,0x3ec43f80,0xbf6d0000,0xbec4bf80,
0xbec43f35,0xbf6dbf35,0x3ec4bf35,0x3f6d3f35,0x3f750000,0x3e953f80,0xbf62bf35,0x3ef1bf35,0xbf223f0e,0xbf46bf55,0x3f7f3e48,0x3dc93f7b,
0x3dc9bf6d,0x3f7f3ec4,0xbf463ec4,0xbf22bf6d,0x3ef13f7b,0xbf623e48,0x3e95bf55,0x3f753f0e,0xbe48bf80,0x3f7b8000,0xbf7b0000,0xbe48bf80,
0x3f0e3f6d,0xbf553ec4,0x3f55bec4,0x3f0e3f6d,0xbf55bf35,0x3f0ebf35,0xbf0e3f35,0xbf55bf35,0x3f7b3ec4,0xbe483f6d,0x3e48bf6d,0x3f7b3ec4,
0xbf7f0000,0xbdc9bf80,0xbf223f35,0xbf46bf35,0x3f75be48,0x3e953f7b,0x3ef1bf55,0x3f623f0e,0xbf623ec4,0xbef1bf6d,0xbe953f6d,0xbf75bec4,
0x3f46bf0e,0x3f223f55,0x3dc9bf7b,0x3f7f3e48,0x3f80,0xbf808000,0x3f80,0xbf808000,0xbf80,0x3f808000,0xbf80,0x3f808000,
0x3f80,0xbf808000,0x3f80,0xbf808000,0xbf80,0x3f808000,0xbf80,0x3f808000,0x3f7f0000,0xbdc93f80,0x3f223f35,0xbf463f35,
0xbf75be48,0x3e95bf7b,0xbef1bf55,0x3f62bf0e,0x3f623ec4,0xbef13f6d,0x3e953f6d,0xbf753ec4,0xbf46bf0e,0x3f22bf55,0xbdc9bf7b,0x3f7fbe48,
0x3e48bf80,0x3f7b8000,0x3f7b0000,0xbe483f80,0xbf0e3f6d,0xbf55bec4,0xbf55bec4,0x3f0ebf6d,0x3f55bf35,0x3f0e3f35,0x3f0e3f35,0xbf553f35,
0xbf7b3ec4,0xbe48bf6d,0xbe48bf6d,0x3f7bbec4,0xbf750000,0x3e95bf80,0x3f62bf35,0x3ef13f35,0x3f223f0e,0xbf463f55,0xbf7f3e48,0x3dc9bf7b,
0xbdc9bf6d,0x3f7fbec4,0x3f463ec4,0xbf223f6d,0xbef13f7b,0xbf62be48,0xbe95bf55,0x3f75bf0e,0xbec43f80,0xbf6d8000,0x3ec4bf80,0x3f6d8000,
0x3f6dbf35,0x3ec43f35,0xbf6d3f35,0xbec4bf35,0xbf6d0000,0x3ec4bf80,0x3f6d0000,0xbec43f80,0x3ec43f35,0xbf6d3f35,0xbec4bf35,0x3f6dbf35,
0x3f620000,0xbef13f80,0xbe95bf35,0x3f75bf35,0xbdc9bf55,0x3f7fbf0e,0xbf223f7b,0xbf46be48,0xbf463f6d,0xbf22bec4,0x3f7fbec4,0xbdc93f6d,
0x3f75be48,0xbe953f7b,0xbef1bf0e,0x3f62bf55,0x3f0ebf80,0x3f558000,0xbf550000,0x3f0ebf80,0xbf7b3ec4,0x3e48bf6d,0xbe483f6d,0xbf7b3ec4,
0x3e483f35,0xbf7b3f35,0x3f7bbf35,0x3e483f35,0x3f55bf6d,0x3f0e3ec4,0xbf0ebec4,0x3f55bf6d,0xbf460000,0x3f22bf80,0xbf7f3f35,0xbdc9bf35,
0xbef13f7b,0xbf623e48,0x3e953f0e,0xbf753f55,0x3f75bec4,0xbe953f6d,0x3f62bf6d,0x3ef13ec4,0x3dc9bf55,0x3f7fbf0e,0xbf22be48,0x3f46bf7b,
0xbf353f80,0xbf358000,0xbf353f80,0xbf358000,0x3f350000,0xbf353f80,0x3f350000,0xbf353f80,0x3f35bf80,0x3f358000,0x3f35bf80,0x3f358000,
0xbf350000,0x3f35bf80,0xbf350000,0x3f35bf80,0x3f220000,0xbf463f80,0xbdc93f35,0xbf7f3f35,0x3f62bf7b,0x3ef13e48,0x3f75bf0e,0xbe953f55,
0xbe95bec4,0x3f75bf6d,0x3ef1bf6d,0x3f62bec4,0xbf7f3f55,0xbdc9bf0e,0xbf463e48,0x3f22bf7b,0x3f55bf80,0x3f0e8000,0x3f0e0000,0xbf553f80,
0xbe48bec4,0x3f7bbf6d,0x3f7bbf6d,0x3e483ec4,0xbf7b3f35,0x3e48bf35,0x3e48bf35,0x3f7bbf35,0xbf0e3f6d,0xbf553ec4,0xbf553ec4,0x3f0ebf6d,
0xbef10000,0x3f62bf80,0x3f75bf35,0xbe953f35,0xbf7f3f55,0x3dc9bf0e,0x3f46bf7b,0x3f22be48,0xbf223f6d,0xbf463ec4,0xbdc9bec4,0x3f7fbf6d,
0x3e953e48,0xbf753f7b,0xbf623f0e,0x3ef1bf55,0xbf6d3f80,0xbec48000,0x3f6dbf80,0x3ec48000,0xbec43f35,0xbf6d3f35,0x3ec4bf35,0x3f6dbf35,
0x3ec40000,0xbf6d3f80,0xbec40000,0x3f6dbf80,0x3f6dbf35,0xbec43f35,0xbf6d3f35,0x3ec4bf35,0x3e950000,0xbf753f80,0x3ef1bf35,0x3f62bf35,
0x3f46bf0e,0xbf223f55,0xbdc9be48,0x3f7fbf7b,0x3f7fbf6d,0xbdc93ec4,0xbf223ec4,0x3f46bf6d,0x3f62bf7b,0x3ef1be48,0xbf753f55,0x3e95bf0e,
0x3f7bbf80,0x3e488000,0xbe480000,0x3f7bbf80,0x3f55bf6d,0x3f0ebec4,0xbf0e3ec4,0x3f55bf6d,0x3f0ebf35,0x3f55bf35,0xbf553f35,0x3f0ebf35,
0x3e48bec4,0x3f7bbf6d,0xbf7b3f6d,0x3e48bec4,0xbdc90000,0x3f7fbf80,0xbf463f35,0x3f22bf35,0xbe953e48,0x3f75bf7b,0xbf623f55,0x3ef1bf0e,
0xbef13ec4,0x3f62bf6d,0xbf753f6d,0x3e95bec4,0xbf223f0e,0x3f46bf55,0xbf7f3f7b,0x3dc9be48,0x3f803f80,0xbf353f35,0x3f803f80,0xbf353f35,
0x3f803f80,0xbf353f35,0x3f803f80,0xbf353f35,0x3f803f80,0xbf353f35,0x3f803f80,0xbf353f35,0x3f803f80,0xbf353f35,0x3f803f80,0xbf353f35,
0x3f7e3f80,0xbdfbbcc9,0x3f1d3f31,0xbf4abf39,0x3f733f7a,0xbea1be60,0x3ee63f09,0xbf65bf58,0x3f5f3f6a,0xbefcbecf,0x3e893eb8,0xbf77bf6f,
0x3f423f51,0xbf27bf13,0x3d973e2f,0xbf7fbf7c,0x3f783f80,0xbe79bd49,0xbe79bd49,0xbf78bf80,0x3f4e3f67,0xbf18bedb,0xbf18bedb,0xbf4ebf67,
0x3f043f2c,0xbf5cbf3e,0xbf5cbf3e,0xbf04bf2c,0x3e163eac,0xbf7dbf71,0xbf7dbf71,0xbe16beac,0x3f6f3f7f,0xbeb8bd97,0xbf6abf42,0xbecfbf27,
0x3f133f4a,0xbf51bf1d,0xbf7cbf7e,0x3e2fbdfb,0x3cc93ea1,0xbf80bf73,0xbf39bf65,0x3f313ee6,0xbf09be89,0xbf58bf77,0xbe60befc,0x3f7a3f5f,
0x3f623f7f,0xbef1bdc9,0xbf62bf7f,0x3ef13dc9,0x3e953f22,0xbf75bf46,0xbe95bf22,0x3f753f46,0xbef1bdc9,0xbf62bf7f,0x3ef13dc9,0x3f623f7f,
0xbf75bf46,0xbe95bf22,0x3f753f46,0x3e953f22,0x3f513f7e,0xbf13bdfb,0xbe2fbf1d,0x3f7c3f4a,0xbcc93ee6,0xbf80bf65,0x3f393ea1,0x3f313f73,
0xbf58befc,0xbf09bf5f,0x3f7a3f77,0xbe603e89,0xbf6abf7f,0x3ecfbd97,0x3eb83f42,0xbf6fbf27,0x3f3e3f7d,0xbf2cbe16,0x3f2c3e16,0x3f3e3f7d,
0xbeac3e79,0xbf71bf78,0x3f713f78,0xbeac3e79,0xbf80bf4e,0xbd49bf18,0x3d493f18,0xbf80bf4e,0xbedbbf5c,0x3f673f04,0xbf67bf04,0xbedbbf5c,
0x3f273f7c,0xbf42be2f,0x3f7f3f51,0xbd973f13,0xbf1d3cc9,0xbf4abf80,0x3dfb3f39,0xbf7ebf31,0xbf65bf7a,0x3ee6be60,0xbf73bf09,0xbea1bf58,
0x3e89becf,0x3f773f6a,0xbefcbf6f,0x3f5f3eb8,0x3f0e3f7b,0xbf55be48,0x3f0e3f7b,0xbf55be48,0xbf55be48,0xbf0ebf7b,0xbf55be48,0xbf0ebf7b,
0xbf0ebf7b,0x3f553e48,0xbf0ebf7b,0x3f553e48,0x3f553e48,0x3f0e3f7b,0x3f553e48,0x3f0e3f7b,0x3ee63f7a,0xbf65be60,0xbea13f09,0xbf73bf58,
0xbf77becf,0xbe89bf6a,0xbf5fbf6f,0x3efcbeb8,0xbd97bf51,0x3f7f3f13,0x3f27be2f,0x3f423f7c,0x3f7e3f39,0xbdfb3f31,0x3f1d3f80,0xbf4abcc9,
0x3eac3f78,0xbf71be79,0xbf71be79,0xbeacbf78,0xbf80bf18,0x3d49bf4e,0x3d49bf4e,0x3f803f18,0x3edbbf04,0x3f673f5c,0x3f673f5c,0xbedb3f04,
0x3f2c3f7d,0xbf3e3e16,0xbf3e3e16,0xbf2cbf7d,0x3e603f77,0xbf7abe89,0xbf58bf5f,0x3f09befc,0xbf6fbf42,0x3eb8bf27,0x3f6a3d97,0x3ecf3f7f,
0x3f51bdfb,0x3f133f7e,0xbe2f3f4a,0xbf7cbf1d,0x3cc93f65,0xbf80bee6,0xbf39bf73,0x3f31bea1,0x3dc93f75,0xbf7fbe95,0xbdc9bf75,0x3f7f3e95,
0xbf46bf62,0x3f22bef1,0x3f463f62,0xbf223ef1,0x3f7f3e95,0x3dc93f75,0xbf7fbe95,0xbdc9bf75,0xbf223ef1,0xbf46bf62,0x3f22bef1,0x3f463f62,
0xbcc93f73,0xbf80bea1,0x3f39bee6,0x3f313f65,0xbf09bf77,0x3f58be89,0xbe603f5f,0xbf7abefc,0x3f6a3f27,0xbecf3f42,0xbeb8bf7f,0x3f6fbd97,
0xbf7cbdfb,0xbe2fbf7e,0x3f513f4a,0xbf133f1d,0xbe163f71,0xbf7dbeac,0x3f7d3eac,0xbe163f71,0xbe79bf80,0x3f78bd49,0xbf783d49,0xbe79bf80,
0x3f183f67,0xbf4e3edb,0x3f4ebedb,0x3f183f67,0xbf5cbf2c,0x3f04bf3e,0xbf043f3e,0xbf5cbf2c,0xbe893f6f,0xbf77beb8,0x3efc3f6a,0xbf5f3ecf,
0x3d97bf7c,0x3f7f3e2f,0xbf27bf51,0x3f42bf13,0x3dfb3f80,0xbf7e3cc9,0x3f4a3f31,0xbf1d3f39,0xbea1bf7a,0x3f73be60,0xbf65bf09,0x3ee6bf58,
0xbec43f6d,0xbf6dbec4,0xbec43f6d,0xbf6dbec4,0x3ec4bf6d,0x3f6d3ec4,0x3ec4bf6d,0x3f6d3ec4,0xbec43f6d,0xbf6dbec4,0xbec43f6d,0xbf6dbec4,
0x3ec4bf6d,0x3f6d3ec4,0x3ec4bf6d,0x3f6d3ec4,0xbefc3f6a,0xbf5fbecf,0xbf773eb8,0xbe89bf6f,0x3f27bf51,0x3f423f13,0x3f7fbe2f,0x3d973f7c,
0xbf4a3f31,0xbf1dbf39,0xbf7ebcc9,0x3dfbbf80,0x3f65bf09,0x3ee63f58,0x3f733e60,0xbea13f7a,0xbf183f67,0xbf4ebedb,0xbf4ebedb,0x3f18bf67,
0x3f5cbf2c,0x3f043f3e,0x3f043f3e,0xbf5c3f2c,0xbf7d3eac,0xbe16bf71,0xbe16bf71,0x3f7dbeac,0x3f783d49,0xbe793f80,0xbe793f80,0xbf78bd49,
0xbf313f65,0xbf39bee6,0xbcc9bf73,0x3f80bea1,0x3f7abefc,0x3e603f5f,0xbf093f77,0xbf58be89,0xbf6fbd97,0x3eb8bf7f,0x3f6abf27,0x3ecf3f42,
0x3f133f1d,0xbf513f4a,0xbf7c3dfb,0x3e2fbf7e,0xbf463f62,0xbf22bef1,0x3f46bf62,0x3f223ef1,0x3f7fbe95,0xbdc93f75,0xbf7f3e95,0x3dc9bf75,
0xbf22bef1,0x3f46bf62,0x3f223ef1,0xbf463f62,0xbdc93f75,0xbf7f3e95,0x3dc9bf75,0x3f7fbe95,0xbf583f5f,0xbf09befc,0x3f7abe89,0xbe603f77,
0x3f6abd97,0xbecf3f7f,0xbeb8bf27,0x3f6fbf42,0xbe2fbf4a,0x3f7cbf1d,0xbf133f7e,0xbf51bdfb,0xbf393f73,0xbf31bea1,0x3f80bee6,0xbcc93f65,
0xbf673f5c,0xbedbbf04,0x3edb3f04,0xbf673f5c,0x3f3e3e16,0xbf2c3f7d,0x3f2cbf7d,0x3f3e3e16,0x3eacbf78,0x3f71be79,0xbf713e79,0x3eacbf78,
0xbf803f18,0xbd49bf4e,0x3d493f4e,0xbf803f18,0xbf733f58,0xbea1bf09,0xbee63f7a,0xbf653e60,0x3efc3eb8,0xbf5f3f6f,0x3f77becf,0xbe893f6a,
0x3f42bf7c,0x3f273e2f,0x3d97bf51,0x3f7fbf13,0xbf4a3cc9,0x3f1dbf80,0xbf7e3f39,0xbdfbbf31,0xbf7b3f55,0xbe48bf0e,0xbf7b3f55,0xbe48bf0e,
0x3e483f0e,0xbf7b3f55,0x3e483f0e,0xbf7b3f55,0x3f7bbf55,0x3e483f0e,0x3f7bbf55,0x3e483f0e,0xbe48bf0e,0x3f7bbf55,0xbe48bf0e,0x3f7bbf55,
0xbf7f3f51,0xbd97bf13,0xbf423e2f,0x3f27bf7c,0xbdfb3f39,0xbf7e3f31,0xbf4a3f80,0xbf1dbcc9,0x3f73bf09,0xbea13f58,0x3ee63e60,0xbf653f7a,
0x3efcbf6f,0x3f5fbeb8,0x3f77bf6a,0x3e893ecf,0xbf803f4e,0x3d49bf18,0x3d49bf18,0x3f80bf4e,0xbedb3f5c,0xbf673f04,0xbf673f04,0x3edbbf5c,
0x3f2cbe16,0xbf3e3f7d,0xbf3e3f7d,0xbf2c3e16,0x3f71bf78,0x3eac3e79,0x3eac3e79,0xbf713f78,0xbf7c3f4a,0x3e2fbf1d,0x3f51bf7e,0x3f13bdfb,
0xbf313f73,0xbf393ea1,0xbcc9bee6,0x3f80bf65,0x3e603e89,0xbf7a3f77,0xbf583efc,0x3f09bf5f,0x3f6fbf27,0xbeb83f42,0xbf6a3f7f,0xbecfbd97,
0xbf753f46,0x3e95bf22,0x3f75bf46,0xbe953f22,0xbf623f7f,0xbef13dc9,0x3f62bf7f,0x3ef1bdc9,0xbe953f22,0xbf753f46,0x3e95bf22,0x3f75bf46,
0x3ef1bdc9,0xbf623f7f,0xbef13dc9,0x3f62bf7f,0xbf6a3f42,0x3ecfbf27,0x3eb8bd97,0xbf6f3f7f,0xbf7c3f7e,0xbe2fbdfb,0x3f51bf1d,0xbf133f4a,
0xbf393f65,0xbf313ee6,0x3f80bf73,0xbcc93ea1,0xbe603efc,0xbf7a3f5f,0x3f58bf77,0x3f09be89,0xbf5c3f3e,0x3f04bf2c,0xbf043f2c,0xbf5c3f3e,
0xbf7d3f71,0x3e16beac,0xbe163eac,0xbf7d3f71,0xbf783f80,0xbe793d49,0x3e79bd49,0xbf783f80,0xbf4e3f67,0xbf183edb,0x3f18bedb,0xbf4e3f67,
0xbf4a3f39,0x3f1dbf31,0xbf7e3f80,0xbdfb3cc9,0xbf653f58,0x3ee6bf09,0xbf733f7a,0xbea13e60,0xbf773f6f,0x3e89beb8,0xbf5f3f6a,0xbefc3ecf,
0xbf7f3f7c,0x3d97be2f,0xbf423f51,0xbf273f13,0x3f803f80,0xbf353f35,0x3f803f80,0xbf353f35,0x3f803f80,0xbf353f35,0x3f803f80,0xbf353f35,
0x3f803f80,0xbf353f35,0x3f803f80,0xbf353f35,0x3f803f80,0xbf353f35,0x3f803f80,0xbf353f35,0xbdfbbcc9,0xbf7ebf80,0xbf4abf39,0xbf1dbf31,
0xbea1be60,0xbf73bf7a,0xbf65bf58,0xbee6bf09,0xbefcbecf,0xbf5fbf6a,0xbf77bf6f,0xbe89beb8,0xbf27bf13,0xbf42bf51,0xbf7fbf7c,0xbd97be2f,
0xbf78bf80,0x3e793d49,0x3e793d49,0x3f783f80,0xbf4ebf67,0x3f183edb,0x3f183edb,0x3f4e3f67,0xbf04bf2c,0x3f5c3f3e,0x3f5c3f3e,0x3f043f2c,
0xbe16beac,0x3f7d3f71,0x3f7d3f71,0x3e163eac,0x3eb83d97,0x3f6f3f7f,0x3ecf3f27,0xbf6abf42,0x3f513f1d,0x3f133f4a,0xbe2f3dfb,0xbf7cbf7e,
0x3f803f73,0x3cc93ea1,0xbf31bee6,0xbf39bf65,0x3f583f77,0xbf09be89,0xbf7abf5f,0xbe60befc,0x3f623f7f,0xbef1bdc9,0xbf62bf7f,0x3ef13dc9,
0x3e953f22,0xbf75bf46,0xbe95bf22,0x3f753f46,0xbef1bdc9,0xbf62bf7f,0x3ef13dc9,0x3f623f7f,0xbf75bf46,0xbe95bf22,0x3f753f46,0x3e953f22,
0xbf13bdfb,0xbf51bf7e,0x3f7c3f4a,0x3e2f3f1d,0xbf80bf65,0x3cc9bee6,0x3f313f73,0xbf39bea1,0xbf09bf5f,0x3f583efc,0xbe603e89,0xbf7abf77,
0x3ecfbd97,0x3f6a3f7f,0xbf6fbf27,0xbeb8bf42,0xbf3ebf7d,0x3f2c3e16,0xbf2cbe16,0xbf3ebf7d,0x3eacbe79,0x3f713f78,0xbf71bf78,0x3eacbe79,
0x3f803f4e,0x3d493f18,0xbd49bf18,0x3f803f4e,0x3edb3f5c,0xbf67bf04,0x3f673f04,0x3edb3f5c,0x3f423e2f,0x3f273f7c,0x3d97bf13,0x3f7f3f51,
0x3f4a3f80,0xbf1d3cc9,0x3f7e3f31,0x3dfb3f39,0xbee63e60,0xbf65bf7a,0x3ea13f58,0xbf73bf09,0xbf77bf6a,0x3e89becf,0xbf5fbeb8,0xbefcbf6f,
0x3f0e3f7b,0xbf55be48,0x3f0e3f7b,0xbf55be48,0xbf55be48,0xbf0ebf7b,0xbf55be48,0xbf0ebf7b,0xbf0ebf7b,0x3f553e48,0xbf0ebf7b,0x3f553e48,
0x3f553e48,0x3f0e3f7b,0x3f553e48,0x3f0e3f7b,0xbf65be60,0xbee6bf7a,0xbf73bf58,0x3ea1bf09,0xbe89bf6a,0x3f773ecf,0x3efcbeb8,0x3f5f3f6f,
0x3f7f3f13,0x3d973f51,0x3f423f7c,0xbf273e2f,0xbdfb3f31,0xbf7ebf39,0xbf4abcc9,0xbf1dbf80,0xbeacbf78,0x3f713e79,0x3f713e79,0x3eac3f78,
0x3f803f18,0xbd493f4e,0xbd493f4e,0xbf80bf18,0xbedb3f04,0xbf67bf5c,0xbf67bf5c,0x3edbbf04,0xbf2cbf7d,0x3f3ebe16,0x3f3ebe16,0x3f2c3f7d,
0x3f7a3e89,0x3e603f77,0xbf093efc,0xbf58bf5f,0xbeb83f27,0xbf6fbf42,0xbecfbf7f,0x3f6a3d97,0xbf13bf7e,0x3f51bdfb,0x3f7c3f1d,0xbe2f3f4a,
0x3f803ee6,0x3cc93f65,0xbf313ea1,0xbf39bf73,0x3dc93f75,0xbf7fbe95,0xbdc9bf75,0x3f7f3e95,0xbf46bf62,0x3f22bef1,0x3f463f62,0xbf223ef1,
0x3f7f3e95,0x3dc93f75,0xbf7fbe95,0xbdc9bf75,0xbf223ef1,0xbf46bf62,0x3f22bef1,0x3f463f62,0xbf80bea1,0x3cc9bf73,0x3f313f65,0xbf393ee6,
0x3f58be89,0x3f093f77,0xbf7abefc,0x3e60bf5f,0xbecf3f42,0xbf6abf27,0x3f6fbd97,0x3eb83f7f,0xbe2fbf7e,0x3f7c3dfb,0xbf133f1d,0xbf51bf4a,
0x3e16bf71,0x3f7d3eac,0xbf7dbeac,0x3e16bf71,0x3e793f80,0xbf783d49,0x3f78bd49,0x3e793f80,0xbf18bf67,0x3f4ebedb,0xbf4e3edb,0xbf18bf67,
0x3f5c3f2c,0xbf043f3e,0x3f04bf3e,0x3f5c3f2c,0x3f773eb8,0xbe893f6f,0x3f5fbecf,0x3efc3f6a,0xbf7fbe2f,0x3d97bf7c,0xbf423f13,0xbf27bf51,
0x3f7ebcc9,0x3dfb3f80,0x3f1dbf39,0x3f4a3f31,0xbf733e60,0xbea1bf7a,0xbee63f58,0xbf65bf09,0xbec43f6d,0xbf6dbec4,0xbec43f6d,0xbf6dbec4,
0x3ec4bf6d,0x3f6d3ec4,0x3ec4bf6d,0x3f6d3ec4,0xbec43f6d,0xbf6dbec4,0xbec43f6d,0xbf6dbec4,0x3ec4bf6d,0x3f6d3ec4,0x3ec4bf6d,0x3f6d3ec4,
0xbf5fbecf,0x3efcbf6a,0xbe89bf6f,0x3f77beb8,0x3f423f13,0xbf273f51,0x3d973f7c,0xbf7f3e2f,0xbf1dbf39,0x3f4abf31,0x3dfbbf80,0x3f7e3cc9,
0x3ee63f58,0xbf653f09,0xbea13f7a,0xbf73be60,0x3f18bf67,0x3f4e3edb,0x3f4e3edb,0xbf183f67,0xbf5c3f2c,0xbf04bf3e,0xbf04bf3e,0x3f5cbf2c,
0x3f7dbeac,0x3e163f71,0x3e163f71,0xbf7d3eac,0xbf78bd49,0x3e79bf80,0x3e79bf80,0x3f783d49,0x3f393ee6,0xbf313f65,0xbf803ea1,0xbcc9bf73,
0xbe60bf5f,0x3f7abefc,0x3f583e89,0xbf093f77,0xbeb83f7f,0xbf6fbd97,0xbecfbf42,0x3f6abf27,0x3f51bf4a,0x3f133f1d,0xbe2f3f7e,0xbf7c3dfb,
0xbf463f62,0xbf22bef1,0x3f46bf62,0x3f223ef1,0x3f7fbe95,0xbdc93f75,0xbf7f3e95,0x3dc9bf75,0xbf22bef1,0x3f46bf62,0x3f223ef1,0xbf463f62,
0xbdc93f75,0xbf7f3e95,0x3dc9bf75,0x3f7fbe95,0xbf09befc,0x3f58bf5f,0xbe603f77,0xbf7a3e89,0xbecf3f7f,0xbf6a3d97,0x3f6fbf42,0x3eb83f27,
0x3f7cbf1d,0x3e2f3f4a,0xbf51bdfb,0x3f13bf7e,0xbf31bea1,0x3f39bf73,0xbcc93f65,0xbf803ee6,0x3f67bf5c,0x3edb3f04,0xbedbbf04,0x3f67bf5c,
0xbf3ebe16,0x3f2cbf7d,0xbf2c3f7d,0xbf3ebe16,0xbeac3f78,0xbf713e79,0x3f71be79,0xbeac3f78,0x3f80bf18,0x3d493f4e,0xbd49bf4e,0x3f80bf18,
0x3ea13f09,0xbf733f58,0x3f65be60,0xbee63f7a,0x3f5fbf6f,0x3efc3eb8,0x3e89bf6a,0x3f77becf,0xbf27be2f,0x3f42bf7c,0xbf7f3f13,0x3d97bf51,
0xbf1d3f80,0xbf4a3cc9,0x3dfb3f31,0xbf7e3f39,0xbf7b3f55,0xbe48bf0e,0xbf7b3f55,0xbe48bf0e,0x3e483f0e,0xbf7b3f55,0x3e483f0e,0xbf7b3f55,
0x3f7bbf55,0x3e483f0e,0x3f7bbf55,0x3e483f0e,0xbe48bf0e,0x3f7bbf55,0xbe48bf0e,0x3f7bbf55,0xbd97bf13,0x3f7fbf51,0x3f27bf7c,0x3f42be2f,
0xbf7e3f31,0x3dfbbf39,0xbf1dbcc9,0x3f4abf80,0xbea13f58,0xbf733f09,0xbf653f7a,0xbee6be60,0x3f5fbeb8,0xbefc3f6f,0x3e893ecf,0xbf773f6a,
0x3f80bf4e,0xbd493f18,0xbd493f18,0xbf803f4e,0x3edbbf5c,0x3f67bf04,0x3f67bf04,0xbedb3f5c,0xbf2c3e16,0x3f3ebf7d,0x3f3ebf7d,0x3f2cbe16,
0xbf713f78,0xbeacbe79,0xbeacbe79,0x3f71bf78,0xbe2f3f1d,0xbf7c3f4a,0xbf133dfb,0x3f51bf7e,0x3f39bea1,0xbf313f73,0xbf803f65,0xbcc9bee6,
0x3f7abf77,0x3e603e89,0xbf093f5f,0xbf583efc,0x3eb8bf42,0x3f6fbf27,0x3ecf3d97,0xbf6a3f7f,0xbf753f46,0x3e95bf22,0x3f75bf46,0xbe953f22,
0xbf623f7f,0xbef13dc9,0x3f62bf7f,0x3ef1bdc9,0xbe953f22,0xbf753f46,0x3e95bf22,0x3f75bf46,0x3ef1bdc9,0xbf623f7f,0xbef13dc9,0x3f62bf7f,
0x3ecfbf27,0x3f6abf42,0xbf6f3f7f,0xbeb83d97,0xbe2fbdfb,0x3f7cbf7e,0xbf133f4a,0xbf513f1d,0xbf313ee6,0x3f39bf65,0xbcc93ea1,0xbf803f73,
0xbf7a3f5f,0x3e60befc,0x3f09be89,0xbf583f77,0x3f5cbf3e,0xbf043f2c,0x3f04bf2c,0x3f5cbf3e,0x3f7dbf71,0xbe163eac,0x3e16beac,0x3f7dbf71,
0x3f78bf80,0x3e79bd49,0xbe793d49,0x3f78bf80,0x3f4ebf67,0x3f18bedb,0xbf183edb,0x3f4ebf67,0xbf1d3f31,0xbf4a3f39,0x3dfbbcc9,0xbf7e3f80,
0xbee63f09,0xbf653f58,0x3ea1be60,0xbf733f7a,0xbe893eb8,0xbf773f6f,0x3efcbecf,0xbf5f3f6a,0xbd973e2f,0xbf7f3f7c,0x3f27bf13,0xbf423f51,
0x3f803f80,0xbf353f35,0x3f803f80,0xbf353f35,0x3f803f80,0xbf353f35,0x3f803f80,0xbf353f35,0x3f803f80,0xbf353f35,0x3f803f80,0xbf353f35,
0x3f803f80,0xbf353f35,0x3f803f80,0xbf353f35,0xbf7ebf80,0x3dfb3cc9,0xbf1dbf31,0x3f4a3f39,0xbf73bf7a,0x3ea13e60,0xbee6bf09,0x3f653f58,
0xbf5fbf6a,0x3efc3ecf,0xbe89beb8,0x3f773f6f,0xbf42bf51,0x3f273f13,0xbd97be2f,0x3f7f3f7c,0x3f783f80,0xbe79bd49,0xbe79bd49,0xbf78bf80,
0x3f4e3f67,0xbf18bedb,0xbf18bedb,0xbf4ebf67,0x3f043f2c,0xbf5cbf3e,0xbf5cbf3e,0xbf04bf2c,0x3e163eac,0xbf7dbf71,0xbf7dbf71,0xbe16beac,
0xbf6fbf7f,0x3eb83d97,0x3f6a3f42,0x3ecf3f27,0xbf13bf4a,0x3f513f1d,0x3f7c3f7e,0xbe2f3dfb,0xbcc9bea1,0x3f803f73,0x3f393f65,0xbf31bee6,
0x3f093e89,0x3f583f77,0x3e603efc,0xbf7abf5f,0x3f623f7f,0xbef1bdc9,0xbf62bf7f,0x3ef13dc9,0x3e953f22,0xbf75bf46,0xbe95bf22,0x3f753f46,
0xbef1bdc9,0xbf62bf7f,0x3ef13dc9,0x3f623f7f,0xbf75bf46,0xbe95bf22,0x3f753f46,0x3e953f22,0xbf51bf7e,0x3f133dfb,0x3e2f3f1d,0xbf7cbf4a,
0x3cc9bee6,0x3f803f65,0xbf39bea1,0xbf31bf73,0x3f583efc,0x3f093f5f,0xbf7abf77,0x3e60be89,0x3f6a3f7f,0xbecf3d97,0xbeb8bf42,0x3f6f3f27,
0x3f3e3f7d,0xbf2cbe16,0x3f2c3e16,0x3f3e3f7d,0xbeac3e79,0xbf71bf78,0x3f713f78,0xbeac3e79,0xbf80bf4e,0xbd49bf18,0x3d493f18,0xbf80bf4e,
0xbedbbf5c,0x3f673f04,0xbf67bf04,0xbedbbf5c,0xbf27bf7c,0x3f423e2f,0xbf7fbf51,0x3d97bf13,0x3f1dbcc9,0x3f4a3f80,0xbdfbbf39,0x3f7e3f31,
0x3f653f7a,0xbee63e60,0x3f733f09,0x3ea13f58,0xbe893ecf,0xbf77bf6a,0x3efc3f6f,0xbf5fbeb8,0x3f0e3f7b,0xbf55be48,0x3f0e3f7b,0xbf55be48,
0xbf55be48,0xbf0ebf7b,0xbf55be48,0xbf0ebf7b,0xbf0ebf7b,0x3f553e48,0xbf0ebf7b,0x3f553e48,0x3f553e48,0x3f0e3f7b,0x3f553e48,0x3f0e3f7b,
0xbee6bf7a,0x3f653e60,0x3ea1bf09,0x3f733f58,0x3f773ecf,0x3e893f6a,0x3f5f3f6f,0xbefc3eb8,0x3d973f51,0xbf7fbf13,0xbf273e2f,0xbf42bf7c,
0xbf7ebf39,0x3dfbbf31,0xbf1dbf80,0x3f4a3cc9,0x3eac3f78,0xbf71be79,0xbf71be79,0xbeacbf78,0xbf80bf18,0x3d49bf4e,0x3d49bf4e,0x3f803f18,
0x3edbbf04,0x3f673f5c,0x3f673f5c,0xbedb3f04,0x3f2c3f7d,0xbf3e3e16,0xbf3e3e16,0xbf2cbf7d,0xbe60bf77,0x3f7a3e89,0x3f583f5f,0xbf093efc,
0x3f6f3f42,0xbeb83f27,0xbf6abd97,0xbecfbf7f,0xbf513dfb,0xbf13bf7e,0x3e2fbf4a,0x3f7c3f1d,0xbcc9bf65,0x3f803ee6,0x3f393f73,0xbf313ea1,
0x3dc93f75,0xbf7fbe95,0xbdc9bf75,0x3f7f3e95,0xbf46bf62,0x3f22bef1,0x3f463f62,0xbf223ef1,0x3f7f3e95,0x3dc93f75,0xbf7fbe95,0xbdc9bf75,
0xbf223ef1,0xbf46bf62,0x3f22bef1,0x3f463f62,0x3cc9bf73,0x3f803ea1,0xbf393ee6,0xbf31bf65,0x3f093f77,0xbf583e89,0x3e60bf5f,0x3f7a3efc,
0xbf6abf27,0x3ecfbf42,0x3eb83f7f,0xbf6f3d97,0x3f7c3dfb,0x3e2f3f7e,0xbf51bf4a,0x3f13bf1d,0xbe163f71,0xbf7dbeac,0x3f7d3eac,0xbe163f71,
0xbe79bf80,0x3f78bd49,0xbf783d49,0xbe79bf80,0x3f183f67,0xbf4e3edb,0x3f4ebedb,0x3f183f67,0xbf5cbf2c,0x3f04bf3e,0xbf043f3e,0xbf5cbf2c,
0x3e89bf6f,0x3f773eb8,0xbefcbf6a,0x3f5fbecf,0xbd973f7c,0xbf7fbe2f,0x3f273f51,0xbf423f13,0xbdfbbf80,0x3f7ebcc9,0xbf4abf31,0x3f1dbf39,
0x3ea13f7a,0xbf733e60,0x3f653f09,0xbee63f58,0xbec43f6d,0xbf6dbec4,0xbec43f6d,0xbf6dbec4,0x3ec4bf6d,0x3f6d3ec4,0x3ec4bf6d,0x3f6d3ec4,
0xbec43f6d,0xbf6dbec4,0xbec43f6d,0xbf6dbec4,0x3ec4bf6d,0x3f6d3ec4,0x3ec4bf6d,0x3f6d3ec4,0x3efcbf6a,0x3f5f3ecf,0x3f77beb8,0x3e893f6f,
0xbf273f51,0xbf42bf13,0xbf7f3e2f,0xbd97bf7c,0x3f4abf31,0x3f1d3f39,0x3f7e3cc9,0xbdfb3f80,0xbf653f09,0xbee6bf58,0xbf73be60,0x3ea1bf7a,
0xbf183f67,0xbf4ebedb,0xbf4ebedb,0x3f18bf67,0x3f5cbf2c,0x3f043f3e,0x3f043f3e,0xbf5c3f2c,0xbf7d3eac,0xbe16bf71,0xbe16bf71,0x3f7dbeac,
0x3f783d49,0xbe793f80,0xbe793f80,0xbf78bd49,0x3f31bf65,0x3f393ee6,0x3cc93f73,0xbf803ea1,0xbf7a3efc,0xbe60bf5f,0x3f09bf77,0x3f583e89,
0x3f6f3d97,0xbeb83f7f,0xbf6a3f27,0xbecfbf42,0xbf13bf1d,0x3f51bf4a,0x3f7cbdfb,0xbe2f3f7e,0xbf463f62,0xbf22bef1,0x3f46bf62,0x3f223ef1,
0x3f7fbe95,0xbdc93f75,0xbf7f3e95,0x3dc9bf75,0xbf22bef1,0x3f46bf62,0x3f223ef1,0xbf463f62,0xbdc93f75,0xbf7f3e95,0x3dc9bf75,0x3f7fbe95,
0x3f58bf5f,0x3f093efc,0xbf7a3e89,0x3e60bf77,0xbf6a3d97,0x3ecfbf7f,0x3eb83f27,0xbf6f3f42,0x3e2f3f4a,0xbf7c3f1d,0x3f13bf7e,0x3f513dfb,
0x3f39bf73,0x3f313ea1,0xbf803ee6,0x3cc9bf65,0xbf673f5c,0xbedbbf04,0x3edb3f04,0xbf673f5c,0x3f3e3e16,0xbf2c3f7d,0x3f2cbf7d,0x3f3e3e16,
0x3eacbf78,0x3f71be79,0xbf713e79,0x3eacbf78,0xbf803f18,0xbd49bf4e,0x3d493f4e,0xbf803f18,0x3f73bf58,0x3ea13f09,0x3ee6bf7a,0x3f65be60,
0xbefcbeb8,0x3f5fbf6f,0xbf773ecf,0x3e89bf6a,0xbf423f7c,0xbf27be2f,0xbd973f51,0xbf7f3f13,0x3f4abcc9,0xbf1d3f80,0x3f7ebf39,0x3dfb3f31,
0xbf7b3f55,0xbe48bf0e,0xbf7b3f55,0xbe48bf0e,0x3e483f0e,0xbf7b3f55,0x3e483f0e,0xbf7b3f55,0x3f7bbf55,0x3e483f0e,0x3f7bbf55,0x3e483f0e,
0xbe48bf0e,0x3f7bbf55,0xbe48bf0e,0x3f7bbf55,0x3f7fbf51,0x3d973f13,0x3f42be2f,0xbf273f7c,0x3dfbbf39,0x3f7ebf31,0x3f4abf80,0x3f1d3cc9,
0xbf733f09,0x3ea1bf58,0xbee6be60,0x3f65bf7a,0xbefc3f6f,0xbf5f3eb8,0xbf773f6a,0xbe89becf,0xbf803f4e,0x3d49bf18,0x3d49bf18,0x3f80bf4e,
0xbedb3f5c,0xbf673f04,0xbf673f04,0x3edbbf5c,0x3f2cbe16,0xbf3e3f7d,0xbf3e3f7d,0xbf2c3e16,0x3f71bf78,0x3eac3e79,0x3eac3e79,0xbf713f78,
0x3f7cbf4a,0xbe2f3f1d,0xbf513f7e,0xbf133dfb,0x3f31bf73,0x3f39bea1,0x3cc93ee6,0xbf803f65,0xbe60be89,0x3f7abf77,0x3f58befc,0xbf093f5f,
0xbf6f3f27,0x3eb8bf42,0x3f6abf7f,0x3ecf3d97,0xbf753f46,0x3e95bf22,0x3f75bf46,0xbe953f22,0xbf623f7f,0xbef13dc9,0x3f62bf7f,0x3ef1bdc9,
0xbe953f22,0xbf753f46,0x3e95bf22,0x3f75bf46,0x3ef1bdc9,0xbf623f7f,0xbef13dc9,0x3f62bf7f,0x3f6abf42,0xbecf3f27,0xbeb83d97,0x3f6fbf7f,
0x3f7cbf7e,0x3e2f3dfb,0xbf513f1d,0x3f13bf4a,0x3f39bf65,0x3f31bee6,0xbf803f73,0x3cc9bea1,0x3e60befc,0x3f7abf5f,0xbf583f77,0xbf093e89,
0xbf5c3f3e,0x3f04bf2c,0xbf043f2c,0xbf5c3f3e,0xbf7d3f71,0x3e16beac,0xbe163eac,0xbf7d3f71,0xbf783f80,0xbe793d49,0x3e79bd49,0xbf783f80,
0xbf4e3f67,0xbf183edb,0x3f18bedb,0xbf4e3f67,0x3f4abf39,0xbf1d3f31,0x3f7ebf80,0x3dfbbcc9,0x3f65bf58,0xbee63f09,0x3f73bf7a,0x3ea1be60,
0x3f77bf6f,0xbe893eb8,0x3f5fbf6a,0x3efcbecf,0x3f7fbf7c,0xbd973e2f,0x3f42bf51,0x3f27bf13,0x3f803f80,0xbf353f35,0x3f803f80,0xbf353f35,
0x3f803f80,0xbf353f35,0x3f803f80,0xbf353f35,0x3f803f80,0xbf353f35,0x3f803f80,0xbf353f35,0x3f803f80,0xbf353f35,0x3f803f80,0xbf353f35,
0x3dfb3cc9,0x3f7e3f80,0x3f4a3f39,0x3f1d3f31,0x3ea13e60,0x3f733f7a,0x3f653f58,0x3ee63f09,0x3efc3ecf,0x3f5f3f6a,0x3f773f6f,0x3e893eb8,
0x3f273f13,0x3f423f51,0x3f7f3f7c,0x3d973e2f,0xbf78bf80,0x3e793d49,0x3e793d49,0x3f783f80,0xbf4ebf67,0x3f183edb,0x3f183edb,0x3f4e3f67,
0xbf04bf2c,0x3f5c3f3e,0x3f5c3f3e,0x3f043f2c,0xbe16beac,0x3f7d3f71,0x3f7d3f71,0x3e163eac,0xbeb8bd97,0xbf6fbf7f,0xbecfbf27,0x3f6a3f42,
0xbf51bf1d,0xbf13bf4a,0x3e2fbdfb,0x3f7c3f7e,0xbf80bf73,0xbcc9bea1,0x3f313ee6,0x3f393f65,0xbf58bf77,0x3f093e89,0x3f7a3f5f,0x3e603efc,
0x3f623f7f,0xbef1bdc9,0xbf62bf7f,0x3ef13dc9,0x3e953f22,0xbf75bf46,0xbe95bf22,0x3f753f46,0xbef1bdc9,0xbf62bf7f,0x3ef13dc9,0x3f623f7f,
0xbf75bf46,0xbe95bf22,0x3f753f46,0x3e953f22,0x3f133dfb,0x3f513f7e,0xbf7cbf4a,0xbe2fbf1d,0x3f803f65,0xbcc93ee6,0xbf31bf73,0x3f393ea1,
0x3f093f5f,0xbf58befc,0x3e60be89,0x3f7a3f77,0xbecf3d97,0xbf6abf7f,0x3f6f3f27,0x3eb83f42,0xbf3ebf7d,0x3f2c3e16,0xbf2cbe16,0xbf3ebf7d,
0x3eacbe79,0x3f713f78,0xbf71bf78,0x3eacbe79,0x3f803f4e,0x3d493f18,0xbd49bf18,0x3f803f4e,0x3edb3f5c,0xbf67bf04,0x3f673f04,0x3edb3f5c,
0xbf42be2f,0xbf27bf7c,0xbd973f13,0xbf7fbf51,0xbf4abf80,0x3f1dbcc9,0xbf7ebf31,0xbdfbbf39,0x3ee6be60,0x3f653f7a,0xbea1bf58,0x3f733f09,
0x3f773f6a,0xbe893ecf,0x3f5f3eb8,0x3efc3f6f,0x3f0e3f7b,0xbf55be48,0x3f0e3f7b,0xbf55be48,0xbf55be48,0xbf0ebf7b,0xbf55be48,0xbf0ebf7b,
0xbf0ebf7b,0x3f553e48,0xbf0ebf7b,0x3f553e48,0x3f553e48,0x3f0e3f7b,0x3f553e48,0x3f0e3f7b,0x3f653e60,0x3ee63f7a,0x3f733f58,0xbea13f09,
0x3e893f6a,0xbf77becf,0xbefc3eb8,0xbf5fbf6f,0xbf7fbf13,0xbd97bf51,0xbf42bf7c,0x3f27be2f,0x3dfbbf31,0x3f7e3f39,0x3f4a3cc9,0x3f1d3f80,
0xbeacbf78,0x3f713e79,0x3f713e79,0x3eac3f78,0x3f803f18,0xbd493f4e,0xbd493f4e,0xbf80bf18,0xbedb3f04,0xbf67bf5c,0xbf67bf5c,0x3edbbf04,
0xbf2cbf7d,0x3f3ebe16,0x3f3ebe16,0x3f2c3f7d,0xbf7abe89,0xbe60bf77,0x3f09befc,0x3f583f5f,0x3eb8bf27,0x3f6f3f42,0x3ecf3f7f,0xbf6abd97,
0x3f133f7e,0xbf513dfb,0xbf7cbf1d,0x3e2fbf4a,0xbf80bee6,0xbcc9bf65,0x3f31bea1,0x3f393f73,0x3dc93f75,0xbf7fbe95,0xbdc9bf75,0x3f7f3e95,
0xbf46bf62,0x3f22bef1,0x3f463f62,0xbf223ef1,0x3f7f3e95,0x3dc93f75,0xbf7fbe95,0xbdc9bf75,0xbf223ef1,0xbf46bf62,0x3f22bef1,0x3f463f62,
0x3f803ea1,0xbcc93f73,0xbf31bf65,0x3f39bee6,0xbf583e89,0xbf09bf77,0x3f7a3efc,0xbe603f5f,0x3ecfbf42,0x3f6a3f27,0xbf6f3d97,0xbeb8bf7f,
0x3e2f3f7e,0xbf7cbdfb,0x3f13bf1d,0x3f513f4a,0x3e16bf71,0x3f7d3eac,0xbf7dbeac,0x3e16bf71,0x3e793f80,0xbf783d49,0x3f78bd49,0x3e793f80,
0xbf18bf67,0x3f4ebedb,0xbf4e3edb,0xbf18bf67,0x3f5c3f2c,0xbf043f3e,0x3f04bf3e,0x3f5c3f2c,0xbf77beb8,0x3e89bf6f,0xbf5f3ecf,0xbefcbf6a,
0x3f7f3e2f,0xbd973f7c,0x3f42bf13,0x3f273f51,0xbf7e3cc9,0xbdfbbf80,0xbf1d3f39,0xbf4abf31,0x3f73be60,0x3ea13f7a,0x3ee6bf58,0x3f653f09,
0xbec43f6d,0xbf6dbec4,0xbec43f6d,0xbf6dbec4,0x3ec4bf6d,0x3f6d3ec4,0x3ec4bf6d,0x3f6d3ec4,0xbec43f6d,0xbf6dbec4,0xbec43f6d,0xbf6dbec4,
0x3ec4bf6d,0x3f6d3ec4,0x3ec4bf6d,0x3f6d3ec4,0x3f5f3ecf,0xbefc3f6a,0x3e893f6f,0xbf773eb8,0xbf42bf13,0x3f27bf51,0xbd97bf7c,0x3f7fbe2f,
0x3f1d3f39,0xbf4a3f31,0xbdfb3f80,0xbf7ebcc9,0xbee6bf58,0x3f65bf09,0x3ea1bf7a,0x3f733e60,0x3f18bf67,0x3f4e3edb,0x3f4e3edb,0xbf183f67,
0xbf5c3f2c,0xbf04bf3e,0xbf04bf3e,0x3f5cbf2c,0x3f7dbeac,0x3e163f71,0x3e163f71,0xbf7d3eac,0xbf78bd49,0x3e79bf80,0x3e79bf80,0x3f783d49,
0xbf39bee6,0x3f31bf65,0x3f80bea1,0x3cc93f73,0x3e603f5f,0xbf7a3efc,0xbf58be89,0x3f09bf77,0x3eb8bf7f,0x3f6f3d97,0x3ecf3f42,0xbf6a3f27,
0xbf513f4a,0xbf13bf1d,0x3e2fbf7e,0x3f7cbdfb,0xbf463f62,0xbf22bef1,0x3f46bf62,0x3f223ef1,0x3f7fbe95,0xbdc93f75,0xbf7f3e95,0x3dc9bf75,
0xbf22bef1,0x3f46bf62,0x3f223ef1,0xbf463f62,0xbdc93f75,0xbf7f3e95,0x3dc9bf75,0x3f7fbe95,0x3f093efc,0xbf583f5f,0x3e60bf77,0x3f7abe89,
0x3ecfbf7f,0x3f6abd97,0xbf6f3f42,0xbeb8bf27,0xbf7c3f1d,0xbe2fbf4a,0x3f513dfb,0xbf133f7e,0x3f313ea1,0xbf393f73,0x3cc9bf65,0x3f80bee6,
0x3f67bf5c,0x3edb3f04,0xbedbbf04,0x3f67bf5c,0xbf3ebe16,0x3f2cbf7d,0xbf2c3f7d,0xbf3ebe16,0xbeac3f78,0xbf713e79,0x3f71be79,0xbeac3f78,
0x3f80bf18,0x3d493f4e,0xbd49bf4e,0x3f80bf18,0xbea1bf09,0x3f73bf58,0xbf653e60,0x3ee6bf7a,0xbf5f3f6f,0xbefcbeb8,0xbe893f6a,0xbf773ecf,
0x3f273e2f,0xbf423f7c,0x3f7fbf13,0xbd973f51,0x3f1dbf80,0x3f4abcc9,0xbdfbbf31,0x3f7ebf39,0xbf7b3f55,0xbe48bf0e,0xbf7b3f55,0xbe48bf0e,
0x3e483f0e,0xbf7b3f55,0x3e483f0e,0xbf7b3f55,0x3f7bbf55,0x3e483f0e,0x3f7bbf55,0x3e483f0e,0xbe48bf0e,0x3f7bbf55,0xbe48bf0e,0x3f7bbf55,
0x3d973f13,0xbf7f3f51,0xbf273f7c,0xbf423e2f,0x3f7ebf31,0xbdfb3f39,0x3f1d3cc9,0xbf4a3f80,0x3ea1bf58,0x3f73bf09,0x3f65bf7a,0x3ee63e60,
0xbf5f3eb8,0x3efcbf6f,0xbe89becf,0x3f77bf6a,0x3f80bf4e,0xbd493f18,0xbd493f18,0xbf803f4e,0x3edbbf5c,0x3f67bf04,0x3f67bf04,0xbedb3f5c,
0xbf2c3e16,0x3f3ebf7d,0x3f3ebf7d,0x3f2cbe16,0xbf713f78,0xbeacbe79,0xbeacbe79,0x3f71bf78,0x3e2fbf1d,0x3f7cbf4a,0x3f13bdfb,0xbf513f7e,
0xbf393ea1,0x3f31bf73,0x3f80bf65,0x3cc93ee6,0xbf7a3f77,0xbe60be89,0x3f09bf5f,0x3f58befc,0xbeb83f42,0xbf6f3f27,0xbecfbd97,0x3f6abf7f,
0xbf753f46,0x3e95bf22,0x3f75bf46,0xbe953f22,0xbf623f7f,0xbef13dc9,0x3f62bf7f,0x3ef1bdc9,0xbe953f22,0xbf753f46,0x3e95bf22,0x3f75bf46,
0x3ef1bdc9,0xbf623f7f,0xbef13dc9,0x3f62bf7f,0xbecf3f27,0xbf6a3f42,0x3f6fbf7f,0x3eb8bd97,0x3e2f3dfb,0xbf7c3f7e,0x3f13bf4a,0x3f51bf1d,
0x3f31bee6,0xbf393f65,0x3cc9bea1,0x3f80bf73,0x3f7abf5f,0xbe603efc,0xbf093e89,0x3f58bf77,0x3f5cbf3e,0xbf043f2c,0x3f04bf2c,0x3f5cbf3e,
0x3f7dbf71,0xbe163eac,0x3e16beac,0x3f7dbf71,0x3f78bf80,0x3e79bd49,0xbe793d49,0x3f78bf80,0x3f4ebf67,0x3f18bedb,0xbf183edb,0x3f4ebf67,
0x3f1dbf31,0x3f4abf39,0xbdfb3cc9,0x3f7ebf80,0x3ee6bf09,0x3f65bf58,0xbea13e60,0x3f73bf7a,0x3e89beb8,0x3f77bf6f,0xbefc3ecf,0x3f5fbf6a,
0x3d97be2f,0x3f7fbf7c,0xbf273f13,0x3f42bf51,0x3f803f80,0xbf803f80,0x3f803f80,0xbf803f80,0x3f803f80,0xbf803f80,0x3f803f80,0xbf803f80,
0x3f803f80,0xbf803f80,0x3f803f80,0xbf803f80,0x3f803f80,0xbf803f80,0x3f803f80,0xbf803f80,0x3f7d3f80,0xbe16bd49,0x3f183f2c,0xbf4ebf3e,
0x3f713f78,0xbeacbe79,0x3edb3f04,0xbf67bf5c,0x3f5c3f67,0xbf04bedb,0x3e793eac,0xbf78bf71,0x3f3e3f4e,0xbf2cbf18,0x3d493e16,0xbf80bf7d,
0x3f753f7f,0xbe95bdc9,0xbe95bdc9,0xbf75bf7f,0x3f463f62,0xbf22bef1,0xbf22bef1,0xbf46bf62,0x3ef13f22,0xbf62bf46,0xbf62bf46,0xbef1bf22,
0x3dc93e95,0xbf7fbf75,0xbf7fbf75,0xbdc9be95,0x3f673f7d,0xbedbbe16,0xbf71bf4e,0xbeacbf18,0x3f043f3e,0xbf5cbf2c,0xbf78bf80,0x3e79bd49,
0xbd493e79,0xbf80bf78,0xbf2cbf5c,0x3f3e3f04,0xbf18beac,0xbf4ebf71,0xbe16bedb,0x3f7d3f67,0x3f553f7b,0xbf0ebe48,0xbf55bf7b,0x3f0e3e48,
0x3e483f0e,0xbf7bbf55,0xbe48bf0e,0x3f7b3f55,0xbf0ebe48,0xbf55bf7b,0x3f0e3e48,0x3f553f7b,0xbf7bbf55,0xbe48bf0e,0x3f7b3f55,0x3e483f0e,
0x3f3e3f78,0xbf2cbe79,0xbd49bf04,0x3f803f5c,0xbe163eac,0xbf7dbf71,0x3f4e3edb,0x3f183f67,0xbf67bf18,0xbedbbf4e,0x3f713f7d,0xbeac3e16,
0xbf5cbf80,0x3f043d49,0x3e793f2c,0xbf78bf3e,0x3f223f75,0xbf46be95,0x3f463e95,0x3f223f75,0xbef13dc9,0xbf62bf7f,0x3f623f7f,0xbef13dc9,
0xbf7fbf62,0x3dc9bef1,0xbdc93ef1,0xbf7fbf62,0xbe95bf46,0x3f753f22,0xbf75bf22,0xbe95bf46,0x3f043f71,0xbf5cbeac,0x3f783f67,0xbe793edb,
0xbf3ebe16,0xbf2cbf7d,0xbd493f18,0xbf80bf4e,0xbf4ebf80,0x3f18bd49,0xbf7dbf2c,0xbe16bf3e,0x3edbbe79,0x3f673f78,0xbeacbf5c,0x3f713f04,
0x3ec43f6d,0xbf6dbec4,0x3ec43f6d,0xbf6dbec4,0xbf6dbec4,0xbec4bf6d,0xbf6dbec4,0xbec4bf6d,0xbec4bf6d,0x3f6d3ec4,0xbec4bf6d,0x3f6d3ec4,
0x3f6d3ec4,0x3ec43f6d,0x3f6d3ec4,0x3ec43f6d,0x3e793f67,0xbf78bedb,0xbf043eac,0xbf5cbf71,0xbf80bf18,0xbd49bf4e,0xbf3ebf7d,0x3f2cbe16,
0x3e16bf2c,0x3f7d3f3e,0x3f4e3d49,0x3f183f80,0x3f713f5c,0xbeac3f04,0x3edb3f78,0xbf67be79,0x3dc93f62,0xbf7fbef1,0xbf7fbef1,0xbdc9bf62,
0xbf75bf46,0x3e95bf22,0x3e95bf22,0x3f753f46,0x3f22be95,0x3f463f75,0x3f463f75,0xbf223e95,0x3ef13f7f,0xbf62bdc9,0xbf62bdc9,0xbef1bf7f,
0xbd493f5c,0xbf80bf04,0xbf2cbf78,0x3f3ebe79,0xbf4ebf67,0x3f18bedb,0x3f7d3eac,0x3e163f71,0x3f713e16,0x3eac3f7d,0xbedb3f18,0xbf67bf4e,
0xbe793f3e,0xbf78bf2c,0xbf04bf80,0x3f5cbd49,0xbe483f55,0xbf7bbf0e,0x3e48bf55,0x3f7b3f0e,0xbf0ebf7b,0x3f55be48,0x3f0e3f7b,0xbf553e48,
0x3f7b3f0e,0xbe483f55,0xbf7bbf0e,0x3e48bf55,0xbf553e48,0xbf0ebf7b,0x3f55be48,0x3f0e3f7b,0xbeac3f4e,0xbf71bf18,0x3f67be16,0x3edb3f7d,
0xbe79bf80,0x3f783d49,0xbf043f2c,0xbf5cbf3e,0x3f3e3f5c,0xbf2c3f04,0xbd49bf78,0x3f803e79,0xbf7dbedb,0x3e16bf67,0x3f183f71,0xbf4e3eac,
0xbef13f46,0xbf62bf22,0x3f623f22,0xbef13f46,0x3dc9bf75,0x3f7f3e95,0xbf7fbe95,0x3dc9bf75,0x3e953f7f,0xbf753dc9,0x3f75bdc9,0x3e953f7f,
0xbf22bf62,0x3f46bef1,0xbf463ef1,0xbf22bf62,0xbf183f3e,0xbf4ebf2c,0x3e163f80,0xbf7d3d49,0x3edbbf5c,0x3f673f04,0xbeacbf78,0x3f71be79,
0xbe793f71,0xbf78beac,0x3f043f67,0xbf5c3edb,0x3d49bf7d,0x3f803e16,0xbf2cbf4e,0x3f3ebf18,0xbf353f35,0xbf35bf35,0xbf353f35,0xbf35bf35,
0x3f35bf35,0x3f353f35,0x3f35bf35,0x3f353f35,0xbf353f35,0xbf35bf35,0xbf353f35,0xbf35bf35,0x3f35bf35,0x3f353f35,0x3f35bf35,0x3f353f35,
0xbf4e3f2c,0xbf18bf3e,0xbf7dbd49,0x3e16bf80,0x3f67bf04,0x3edb3f5c,0x3f713e79,0xbeac3f78,0xbf783eac,0xbe79bf71,0xbf5cbedb,0x3f04bf67,
0x3f80be16,0x3d493f7d,0x3f3e3f18,0xbf2c3f4e,0xbf623f22,0xbef1bf46,0xbef1bf46,0x3f62bf22,0x3f7fbe95,0x3dc93f75,0x3dc93f75,0xbf7f3e95,
0xbf75bdc9,0x3e95bf7f,0x3e95bf7f,0x3f753dc9,0x3f463ef1,0xbf223f62,0xbf223f62,0xbf46bef1,0xbf713f18,0xbeacbf4e,0x3edbbf7d,0x3f673e16,
0x3f78bd49,0xbe793f80,0xbf5c3f3e,0xbf04bf2c,0xbf2cbf04,0x3f3ebf5c,0x3f80be79,0xbd493f78,0x3e163f67,0xbf7d3edb,0xbf4ebeac,0x3f18bf71,
0xbf7b3f0e,0xbe48bf55,0x3f7bbf0e,0x3e483f55,0x3f553e48,0xbf0e3f7b,0xbf55be48,0x3f0ebf7b,0xbe48bf55,0x3f7bbf0e,0x3e483f55,0xbf7b3f0e,
0xbf0e3f7b,0xbf55be48,0x3f0ebf7b,0x3f553e48,0xbf803f04,0xbd49bf5c,0x3f3e3e79,0xbf2c3f78,0x3f183edb,0xbf4e3f67,0x3e16bf71,0x3f7dbeac,
0x3eacbf7d,0x3f71be16,0xbf673f4e,0xbedbbf18,0xbf783f2c,0xbe79bf3e,0x3f5c3d49,0xbf043f80,0xbf7f3ef1,0x3dc9bf62,0xbdc93f62,0xbf7f3ef1,
0x3e953f22,0xbf753f46,0x3f75bf46,0x3e953f22,0x3f46bf75,0x3f223e95,0xbf22be95,0x3f46bf75,0xbf623dc9,0x3ef1bf7f,0xbef13f7f,0xbf623dc9,
0xbf783edb,0x3e79bf67,0xbf5c3f71,0xbf04beac,0xbd493f4e,0xbf803f18,0x3f2c3e16,0xbf3e3f7d,0x3f7dbf3e,0x3e163f2c,0x3f18bf80,0x3f4ebd49,
0xbeacbf04,0x3f71bf5c,0xbf673e79,0x3edbbf78,0xbf6d3ec4,0x3ec4bf6d,0xbf6d3ec4,0x3ec4bf6d,0xbec43f6d,0xbf6d3ec4,0xbec43f6d,0xbf6d3ec4,
0x3f6dbec4,0xbec43f6d,0x3f6dbec4,0xbec43f6d,0x3ec4bf6d,0x3f6dbec4,0x3ec4bf6d,0x3f6dbec4,0xbf5c3eac,0x3f04bf71,0xbe79bedb,0x3f78bf67,
0xbf2c3f7d,0xbf3e3e16,0xbf803f4e,0xbd49bf18,0x3f183d49,0xbf4e3f80,0xbe163f3e,0xbf7d3f2c,0x3f67bf78,0x3edb3e79,0x3f71bf04,0xbeac3f5c,
0xbf463e95,0x3f22bf75,0x3f22bf75,0x3f46be95,0xbf623f7f,0xbef1bdc9,0xbef1bdc9,0x3f62bf7f,0x3dc93ef1,0xbf7f3f62,0xbf7f3f62,0xbdc9bef1,
0x3f75bf22,0xbe953f46,0xbe953f46,0xbf753f22,0xbf2c3e79,0x3f3ebf78,0x3f80bf5c,0xbd493f04,0xbf7d3f71,0xbe16beac,0x3f18bf67,0x3f4ebedb,
0xbedb3f4e,0xbf673f18,0xbeacbe16,0x3f71bf7d,0x3f04bd49,0xbf5c3f80,0xbf783f3e,0x3e79bf2c,0xbf0e3e48,0x3f55bf7b,0x3f0ebe48,0xbf553f7b,
0xbf7b3f55,0x3e48bf0e,0x3f7bbf55,0xbe483f0e,0xbf553f7b,0xbf0e3e48,0x3f55bf7b,0x3f0ebe48,0xbe483f0e,0xbf7b3f55,0x3e48bf0e,0x3f7bbf55,
0xbedb3e16,0x3f67bf7d,0xbeac3f18,0xbf713f4e,0xbf5c3f2c,0x3f04bf3e,0x3e793d49,0xbf783f80,0xbf803f78,0xbd49be79,0x3f3ebf04,0xbf2c3f5c,
0xbf4e3f71,0xbf183eac,0x3f7dbf67,0xbe163edb,0xbe953dc9,0x3f75bf7f,0xbf753f7f,0xbe953dc9,0xbf223ef1,0x3f46bf62,0xbf463f62,0xbf223ef1,
0xbf623f46,0x3ef1bf22,0xbef13f22,0xbf623f46,0xbf7f3f75,0x3dc9be95,0xbdc93e95,0xbf7f3f75,0xbe163d49,0x3f7dbf80,0xbf4e3f3e,0x3f18bf2c,
0xbeac3e79,0x3f71bf78,0xbf673f5c,0x3edbbf04,0xbf043edb,0x3f5cbf67,0xbf783f71,0x3e79beac,0xbf2c3f18,0x3f3ebf4e,0xbf803f7d,0x3d49be16,
0x3f803f80,0xbf803f80,0x3f803f80,0xbf803f80,0x3f803f80,0xbf803f80,0x3f803f80,0xbf803f80,0x3f803f80,0xbf803f80,0x3f803f80,0xbf803f80,
0x3f803f80,0xbf803f80,0x3f803f80,0xbf803f80,0xbe16bd49,0xbf7dbf80,0xbf4ebf3e,0xbf18bf2c,0xbeacbe79,0xbf71bf78,0xbf67bf5c,0xbedbbf04,
0xbf04bedb,0xbf5cbf67,0xbf78bf71,0xbe79beac,0xbf2cbf18,0xbf3ebf4e,0xbf80bf7d,0xbd49be16,0xbf75bf7f,0x3e953dc9,0x3e953dc9,0x3f753f7f,
0xbf46bf62,0x3f223ef1,0x3f223ef1,0x3f463f62,0xbef1bf22,0x3f623f46,0x3f623f46,0x3ef13f22,0xbdc9be95,0x3f7f3f75,0x3f7f3f75,0x3dc93e95,
0x3edb3e16,0x3f673f7d,0x3eac3f18,0xbf71bf4e,0x3f5c3f2c,0x3f043f3e,0xbe793d49,0xbf78bf80,0x3f803f78,0xbd493e79,0xbf3ebf04,0xbf2cbf5c,
0x3f4e3f71,0xbf18beac,0xbf7dbf67,0xbe16bedb,0x3f553f7b,0xbf0ebe48,0xbf55bf7b,0x3f0e3e48,0x3e483f0e,0xbf7bbf55,0xbe48bf0e,0x3f7b3f55,
0xbf0ebe48,0xbf55bf7b,0x3f0e3e48,0x3f553f7b,0xbf7bbf55,0xbe48bf0e,0x3f7b3f55,0x3e483f0e,0xbf2cbe79,0xbf3ebf78,0x3f803f5c,0x3d493f04,
0xbf7dbf71,0x3e16beac,0x3f183f67,0xbf4ebedb,0xbedbbf4e,0x3f673f18,0xbeac3e16,0xbf71bf7d,0x3f043d49,0x3f5c3f80,0xbf78bf3e,0xbe79bf2c,
0xbf22bf75,0x3f463e95,0xbf46be95,0xbf22bf75,0x3ef1bdc9,0x3f623f7f,0xbf62bf7f,0x3ef1bdc9,0x3f7f3f62,0xbdc93ef1,0x3dc9bef1,0x3f7f3f62,
0x3e953f46,0xbf75bf22,0x3f753f22,0x3e953f46,0x3f5c3eac,0x3f043f71,0x3e79bedb,0x3f783f67,0x3f2c3f7d,0xbf3ebe16,0x3f803f4e,0xbd493f18,
0xbf183d49,0xbf4ebf80,0x3e163f3e,0xbf7dbf2c,0xbf67bf78,0x3edbbe79,0xbf71bf04,0xbeacbf5c,0x3ec43f6d,0xbf6dbec4,0x3ec43f6d,0xbf6dbec4,
0xbf6dbec4,0xbec4bf6d,0xbf6dbec4,0xbec4bf6d,0xbec4bf6d,0x3f6d3ec4,0xbec4bf6d,0x3f6d3ec4,0x3f6d3ec4,0x3ec43f6d,0x3f6d3ec4,0x3ec43f6d,
0xbf78bedb,0xbe79bf67,0xbf5cbf71,0x3f04beac,0xbd49bf4e,0x3f803f18,0x3f2cbe16,0x3f3e3f7d,0x3f7d3f3e,0xbe163f2c,0x3f183f80,0xbf4ebd49,
0xbeac3f04,0xbf71bf5c,0xbf67be79,0xbedbbf78,0xbdc9bf62,0x3f7f3ef1,0x3f7f3ef1,0x3dc93f62,0x3f753f46,0xbe953f22,0xbe953f22,0xbf75bf46,
0xbf223e95,0xbf46bf75,0xbf46bf75,0x3f22be95,0xbef1bf7f,0x3f623dc9,0x3f623dc9,0x3ef13f7f,0x3f803f04,0xbd493f5c,0xbf3e3e79,0xbf2cbf78,
0xbf183edb,0xbf4ebf67,0xbe16bf71,0x3f7d3eac,0xbeacbf7d,0x3f713e16,0x3f673f4e,0xbedb3f18,0x3f783f2c,0xbe793f3e,0xbf5c3d49,0xbf04bf80,
0xbe483f55,0xbf7bbf0e,0x3e48bf55,0x3f7b3f0e,0xbf0ebf7b,0x3f55be48,0x3f0e3f7b,0xbf553e48,0x3f7b3f0e,0xbe483f55,0xbf7bbf0e,0x3e48bf55,
0xbf553e48,0xbf0ebf7b,0x3f55be48,0x3f0e3f7b,0xbf71bf18,0x3eacbf4e,0x3edb3f7d,0xbf673e16,0x3f783d49,0x3e793f80,0xbf5cbf3e,0x3f04bf2c,
0xbf2c3f04,0xbf3ebf5c,0x3f803e79,0x3d493f78,0x3e16bf67,0x3f7d3edb,0xbf4e3eac,0xbf18bf71,0x3ef1bf46,0x3f623f22,0xbf62bf22,0x3ef1bf46,
0xbdc93f75,0xbf7fbe95,0x3f7f3e95,0xbdc93f75,0xbe95bf7f,0x3f75bdc9,0xbf753dc9,0xbe95bf7f,0x3f223f62,0xbf463ef1,0x3f46bef1,0x3f223f62,
0x3f4e3f2c,0xbf183f3e,0x3f7dbd49,0x3e163f80,0xbf67bf04,0x3edbbf5c,0xbf713e79,0xbeacbf78,0x3f783eac,0xbe793f71,0x3f5cbedb,0x3f043f67,
0xbf80be16,0x3d49bf7d,0xbf3e3f18,0xbf2cbf4e,0xbf353f35,0xbf35bf35,0xbf353f35,0xbf35bf35,0x3f35bf35,0x3f353f35,0x3f35bf35,0x3f353f35,
0xbf353f35,0xbf35bf35,0xbf353f35,0xbf35bf35,0x3f35bf35,0x3f353f35,0x3f35bf35,0x3f353f35,0xbf18bf3e,0x3f4ebf2c,0x3e16bf80,0x3f7d3d49,
0x3edb3f5c,0xbf673f04,0xbeac3f78,0xbf71be79,0xbe79bf71,0x3f78beac,0x3f04bf67,0x3f5c3edb,0x3d493f7d,0xbf803e16,0xbf2c3f4e,0xbf3ebf18,
0x3f62bf22,0x3ef13f46,0x3ef13f46,0xbf623f22,0xbf7f3e95,0xbdc9bf75,0xbdc9bf75,0x3f7fbe95,0x3f753dc9,0xbe953f7f,0xbe953f7f,0xbf75bdc9,
0xbf46bef1,0x3f22bf62,0x3f22bf62,0x3f463ef1,0x3eac3f4e,0xbf713f18,0xbf67be16,0x3edbbf7d,0x3e79bf80,0x3f78bd49,0x3f043f2c,0xbf5c3f3e,
0xbf3e3f5c,0xbf2cbf04,0x3d49bf78,0x3f80be79,0x3f7dbedb,0x3e163f67,0xbf183f71,0xbf4ebeac,0xbf7b3f0e,0xbe48bf55,0x3f7bbf0e,0x3e483f55,
0x3f553e48,0xbf0e3f7b,0xbf55be48,0x3f0ebf7b,0xbe48bf55,0x3f7bbf0e,0x3e483f55,0xbf7b3f0e,0xbf0e3f7b,0xbf55be48,0x3f0ebf7b,0x3f553e48,
0xbd49bf5c,0x3f80bf04,0xbf2c3f78,0xbf3ebe79,0xbf4e3f67,0xbf18bedb,0x3f7dbeac,0xbe163f71,0x3f71be16,0xbeac3f7d,0xbedbbf18,0x3f67bf4e,
0xbe79bf3e,0x3f78bf2c,0xbf043f80,0xbf5cbd49,0x3f7fbef1,0xbdc93f62,0x3dc9bf62,0x3f7fbef1,0xbe95bf22,0x3f75bf46,0xbf753f46,0xbe95bf22,
0xbf463f75,0xbf22be95,0x3f223e95,0xbf463f75,0x3f62bdc9,0xbef13f7f,0x3ef1bf7f,0x3f62bdc9,0xbe793f67,0xbf783edb,0x3f043eac,0xbf5c3f71,
0x3f80bf18,0xbd493f4e,0x3f3ebf7d,0x3f2c3e16,0xbe16bf2c,0x3f7dbf3e,0xbf4e3d49,0x3f18bf80,0xbf713f5c,0xbeacbf04,0xbedb3f78,0xbf673e79,
0xbf6d3ec4,0x3ec4bf6d,0xbf6d3ec4,0x3ec4bf6d,0xbec43f6d,0xbf6d3ec4,0xbec43f6d,0xbf6d3ec4,0x3f6dbec4,0xbec43f6d,0x3f6dbec4,0xbec43f6d,
0x3ec4bf6d,0x3f6dbec4,0x3ec4bf6d,0x3f6dbec4,0x3f04bf71,0x3f5cbeac,0x3f78bf67,0x3e793edb,0xbf3e3e16,0x3f2cbf7d,0xbd49bf18,0x3f80bf4e,
0xbf4e3f80,0xbf18bd49,0xbf7d3f2c,0x3e16bf3e,0x3edb3e79,0xbf673f78,0xbeac3f5c,0xbf713f04,0x3f46be95,0xbf223f75,0xbf223f75,0xbf463e95,
0x3f62bf7f,0x3ef13dc9,0x3ef13dc9,0xbf623f7f,0xbdc9bef1,0x3f7fbf62,0x3f7fbf62,0x3dc93ef1,0xbf753f22,0x3e95bf46,0x3e95bf46,0x3f75bf22,
0xbf3e3f78,0xbf2c3e79,0x3d49bf04,0x3f80bf5c,0x3e163eac,0xbf7d3f71,0xbf4e3edb,0x3f18bf67,0x3f67bf18,0xbedb3f4e,0xbf713f7d,0xbeacbe16,
0x3f5cbf80,0x3f04bd49,0xbe793f2c,0xbf783f3e,0xbf0e3e48,0x3f55bf7b,0x3f0ebe48,0xbf553f7b,0xbf7b3f55,0x3e48bf0e,0x3f7bbf55,0xbe483f0e,
0xbf553f7b,0xbf0e3e48,0x3f55bf7b,0x3f0ebe48,0xbe483f0e,0xbf7b3f55,0x3e48bf0e,0x3f7bbf55,0x3f67bf7d,0x3edbbe16,0xbf713f4e,0x3eacbf18,
0x3f04bf3e,0x3f5cbf2c,0xbf783f80,0xbe79bd49,0xbd49be79,0x3f80bf78,0xbf2c3f5c,0xbf3e3f04,0xbf183eac,0x3f4ebf71,0xbe163edb,0xbf7d3f67,
0x3e95bdc9,0xbf753f7f,0x3f75bf7f,0x3e95bdc9,0x3f22bef1,0xbf463f62,0x3f46bf62,0x3f22bef1,0x3f62bf46,0xbef13f22,0x3ef1bf22,0x3f62bf46,
0x3f7fbf75,0xbdc93e95,0x3dc9be95,0x3f7fbf75,0xbf7d3f80,0xbe163d49,0xbf183f2c,0xbf4e3f3e,0xbf713f78,0xbeac3e79,0xbedb3f04,0xbf673f5c,
0xbf5c3f67,0xbf043edb,0xbe793eac,0xbf783f71,0xbf3e3f4e,0xbf2c3f18,0xbd493e16,0xbf803f7d,0x3f803f80,0xbf803f80,0x3f803f80,0xbf803f80,
0x3f803f80,0xbf803f80,0x3f803f80,0xbf803f80,0x3f803f80,0xbf803f80,0x3f803f80,0xbf803f80,0x3f803f80,0xbf803f80,0x3f803f80,0xbf803f80,
0xbf7dbf80,0x3e163d49,0xbf18bf2c,0x3f4e3f3e,0xbf71bf78,0x3eac3e79,0xbedbbf04,0x3f673f5c,0xbf5cbf67,0x3f043edb,0xbe79beac,0x3f783f71,
0xbf3ebf4e,0x3f2c3f18,0xbd49be16,0x3f803f7d,0x3f753f7f,0xbe95bdc9,0xbe95bdc9,0xbf75bf7f,0x3f463f62,0xbf22bef1,0xbf22bef1,0xbf46bf62,
0x3ef13f22,0xbf62bf46,0xbf62bf46,0xbef1bf22,0x3dc93e95,0xbf7fbf75,0xbf7fbf75,0xbdc9be95,0xbf67bf7d,0x3edb3e16,0x3f713f4e,0x3eac3f18,
0xbf04bf3e,0x3f5c3f2c,0x3f783f80,0xbe793d49,0x3d49be79,0x3f803f78,0x3f2c3f5c,0xbf3ebf04,0x3f183eac,0x3f4e3f71,0x3e163edb,0xbf7dbf67,
0x3f553f7b,0xbf0ebe48,0xbf55bf7b,0x3f0e3e48,0x3e483f0e,0xbf7bbf55,0xbe48bf0e,0x3f7b3f55,0xbf0ebe48,0xbf55bf7b,0x3f0e3e48,0x3f553f7b,
0xbf7bbf55,0xbe48bf0e,0x3f7b3f55,0x3e483f0e,0xbf3ebf78,0x3f2c3e79,0x3d493f04,0xbf80bf5c,0x3e16beac,0x3f7d3f71,0xbf4ebedb,0xbf18bf67,
0x3f673f18,0x3edb3f4e,0xbf71bf7d,0x3eacbe16,0x3f5c3f80,0xbf04bd49,0xbe79bf2c,0x3f783f3e,0x3f223f75,0xbf46be95,0x3f463e95,0x3f223f75,
0xbef13dc9,0xbf62bf7f,0x3f623f7f,0xbef13dc9,0xbf7fbf62,0x3dc9bef1,0xbdc93ef1,0xbf7fbf62,0xbe95bf46,0x3f753f22,0xbf75bf22,0xbe95bf46,
0xbf04bf71,0x3f5c3eac,0xbf78bf67,0x3e79bedb,0x3f3e3e16,0x3f2c3f7d,0x3d49bf18,0x3f803f4e,0x3f4e3f80,0xbf183d49,0x3f7d3f2c,0x3e163f3e,
0xbedb3e79,0xbf67bf78,0x3eac3f5c,0xbf71bf04,0x3ec43f6d,0xbf6dbec4,0x3ec43f6d,0xbf6dbec4,0xbf6dbec4,0xbec4bf6d,0xbf6dbec4,0xbec4bf6d,
0xbec4bf6d,0x3f6d3ec4,0xbec4bf6d,0x3f6d3ec4,0x3f6d3ec4,0x3ec43f6d,0x3f6d3ec4,0x3ec43f6d,0xbe79bf67,0x3f783edb,0x3f04beac,0x3f5c3f71,
0x3f803f18,0x3d493f4e,0x3f3e3f7d,0xbf2c3e16,0xbe163f2c,0xbf7dbf3e,0xbf4ebd49,0xbf18bf80,0xbf71bf5c,0x3eacbf04,0xbedbbf78,0x3f673e79,
0x3dc93f62,0xbf7fbef1,0xbf7fbef1,0xbdc9bf62,0xbf75bf46,0x3e95bf22,0x3e95bf22,0x3f753f46,0x3f22be95,0x3f463f75,0x3f463f75,0xbf223e95,
0x3ef13f7f,0xbf62bdc9,0xbf62bdc9,0xbef1bf7f,0x3d49bf5c,0x3f803f04,0x3f2c3f78,0xbf3e3e79,0x3f4e3f67,0xbf183edb,0xbf7dbeac,0xbe16bf71,
0xbf71be16,0xbeacbf7d,0x3edbbf18,0x3f673f4e,0x3e79bf3e,0x3f783f2c,0x3f043f80,0xbf5c3d49,0xbe483f55,0xbf7bbf0e,0x3e48bf55,0x3f7b3f0e,
0xbf0ebf7b,0x3f55be48,0x3f0e3f7b,0xbf553e48,0x3f7b3f0e,0xbe483f55,0xbf7bbf0e,0x3e48bf55,0xbf553e48,0xbf0ebf7b,0x3f55be48,0x3f0e3f7b,
0x3eacbf4e,0x3f713f18,0xbf673e16,0xbedbbf7d,0x3e793f80,0xbf78bd49,0x3f04bf2c,0x3f5c3f3e,0xbf3ebf5c,0x3f2cbf04,0x3d493f78,0xbf80be79,
0x3f7d3edb,0xbe163f67,0xbf18bf71,0x3f4ebeac,0xbef13f46,0xbf62bf22,0x3f623f22,0xbef13f46,0x3dc9bf75,0x3f7f3e95,0xbf7fbe95,0x3dc9bf75,
0x3e953f7f,0xbf753dc9,0x3f75bdc9,0x3e953f7f,0xbf22bf62,0x3f46bef1,0xbf463ef1,0xbf22bf62,0x3f18bf3e,0x3f4e3f2c,0xbe16bf80,0x3f7dbd49,
0xbedb3f5c,0xbf67bf04,0x3eac3f78,0xbf713e79,0x3e79bf71,0x3f783eac,0xbf04bf67,0x3f5cbedb,0xbd493f7d,0xbf80be16,0x3f2c3f4e,0xbf3e3f18,
0xbf353f35,0xbf35bf35,0xbf353f35,0xbf35bf35,0x3f35bf35,0x3f353f35,0x3f35bf35,0x3f353f35,0xbf353f35,0xbf35bf35,0xbf353f35,0xbf35bf35,
0x3f35bf35,0x3f353f35,0x3f35bf35,0x3f353f35,0x3f4ebf2c,0x3f183f3e,0x3f7d3d49,0xbe163f80,0xbf673f04,0xbedbbf5c,0xbf71be79,0x3eacbf78,
0x3f78beac,0x3e793f71,0x3f5c3edb,0xbf043f67,0xbf803e16,0xbd49bf7d,0xbf3ebf18,0x3f2cbf4e,0xbf623f22,0xbef1bf46,0xbef1bf46,0x3f62bf22,
0x3f7fbe95,0x3dc93f75,0x3dc93f75,0xbf7f3e95,0xbf75bdc9,0x3e95bf7f,0x3e95bf7f,0x3f753dc9,0x3f463ef1,0xbf223f62,0xbf223f62,0xbf46bef1,
0x3f71bf18,0x3eac3f4e,0xbedb3f7d,0xbf67be16,0xbf783d49,0x3e79bf80,0x3f5cbf3e,0x3f043f2c,0x3f2c3f04,0xbf3e3f5c,0xbf803e79,0x3d49bf78,
0xbe16bf67,0x3f7dbedb,0x3f4e3eac,0xbf183f71,0xbf7b3f0e,0xbe48bf55,0x3f7bbf0e,0x3e483f55,0x3f553e48,0xbf0e3f7b,0xbf55be48,0x3f0ebf7b,
0xbe48bf55,0x3f7bbf0e,0x3e483f55,0xbf7b3f0e,0xbf0e3f7b,0xbf55be48,0x3f0ebf7b,0x3f553e48,0x3f80bf04,0x3d493f5c,0xbf3ebe79,0x3f2cbf78,
0xbf18bedb,0x3f4ebf67,0xbe163f71,0xbf7d3eac,0xbeac3f7d,0xbf713e16,0x3f67bf4e,0x3edb3f18,0x3f78bf2c,0x3e793f3e,0xbf5cbd49,0x3f04bf80,
0xbf7f3ef1,0x3dc9bf62,0xbdc93f62,0xbf7f3ef1,0x3e953f22,0xbf753f46,0x3f75bf46,0x3e953f22,0x3f46bf75,0x3f223e95,0xbf22be95,0x3f46bf75,
0xbf623dc9,0x3ef1bf7f,0xbef13f7f,0xbf623dc9,0x3f78bedb,0xbe793f67,0x3f5cbf71,0x3f043eac,0x3d49bf4e,0x3f80bf18,0xbf2cbe16,0x3f3ebf7d,
0xbf7d3f3e,0xbe16bf2c,0xbf183f80,0xbf4e3d49,0x3eac3f04,0xbf713f5c,0x3f67be79,0xbedb3f78,0xbf6d3ec4,0x3ec4bf6d,0xbf6d3ec4,0x3ec4bf6d,
0xbec43f6d,0xbf6d3ec4,0xbec43f6d,0xbf6d3ec4,0x3f6dbec4,0xbec43f6d,0x3f6dbec4,0xbec43f6d,0x3ec4bf6d,0x3f6dbec4,0x3ec4bf6d,0x3f6dbec4,
0x3f5cbeac,0xbf043f71,0x3e793edb,0xbf783f67,0x3f2cbf7d,0x3f3ebe16,0x3f80bf4e,0x3d493f18,0xbf18bd49,0x3f4ebf80,0x3e16bf3e,0x3f7dbf2c,
0xbf673f78,0xbedbbe79,0xbf713f04,0x3eacbf5c,0xbf463e95,0x3f22bf75,0x3f22bf75,0x3f46be95,0xbf623f7f,0xbef1bdc9,0xbef1bdc9,0x3f62bf7f,
0x3dc93ef1,0xbf7f3f62,0xbf7f3f62,0xbdc9bef1,0x3f75bf22,0xbe953f46,0xbe953f46,0xbf753f22,0x3f2cbe79,0xbf3e3f78,0xbf803f5c,0x3d49bf04,
0x3f7dbf71,0x3e163eac,0xbf183f67,0xbf4e3edb,0x3edbbf4e,0x3f67bf18,0x3eac3e16,0xbf713f7d,0xbf043d49,0x3f5cbf80,0x3f78bf3e,0xbe793f2c,
0xbf0e3e48,0x3f55bf7b,0x3f0ebe48,0xbf553f7b,0xbf7b3f55,0x3e48bf0e,0x3f7bbf55,0xbe483f0e,0xbf553f7b,0xbf0e3e48,0x3f55bf7b,0x3f0ebe48,
0xbe483f0e,0xbf7b3f55,0x3e48bf0e,0x3f7bbf55,0x3edbbe16,0xbf673f7d,0x3eacbf18,0x3f71bf4e,0x3f5cbf2c,0xbf043f3e,0xbe79bd49,0x3f78bf80,
0x3f80bf78,0x3d493e79,0xbf3e3f04,0x3f2cbf5c,0x3f4ebf71,0x3f18beac,0xbf7d3f67,0x3e16bedb,0xbe953dc9,0x3f75bf7f,0xbf753f7f,0xbe953dc9,
0xbf223ef1,0x3f46bf62,0xbf463f62,0xbf223ef1,0xbf623f46,0x3ef1bf22,0xbef13f22,0xbf623f46,0xbf7f3f75,0x3dc9be95,0xbdc93e95,0xbf7f3f75,
0x3e16bd49,0xbf7d3f80,0x3f4ebf3e,0xbf183f2c,0x3eacbe79,0xbf713f78,0x3f67bf5c,0xbedb3f04,0x3f04bedb,0xbf5c3f67,0x3f78bf71,0xbe793eac,
0x3f2cbf18,0xbf3e3f4e,0x3f80bf7d,0xbd493e16,0x3f803f80,0xbf803f80,0x3f803f80,0xbf803f80,0x3f803f80,0xbf803f80,0x3f803f80,0xbf803f80,
0x3f803f80,0xbf803f80,0x3f803f80,0xbf803f80,0x3f803f80,0xbf803f80,0x3f803f80,0xbf803f80,0x3e163d49,0x3f7d3f80,0x3f4e3f3e,0x3f183f2c,
0x3eac3e79,0x3f713f78,0x3f673f5c,0x3edb3f04,0x3f043edb,0x3f5c3f67,0x3f783f71,0x3e793eac,0x3f2c3f18,0x3f3e3f4e,0x3f803f7d,0x3d493e16,
0xbf75bf7f,0x3e953dc9,0x3e953dc9,0x3f753f7f,0xbf46bf62,0x3f223ef1,0x3f223ef1,0x3f463f62,0xbef1bf22,0x3f623f46,0x3f623f46,0x3ef13f22,
0xbdc9be95,0x3f7f3f75,0x3f7f3f75,0x3dc93e95,0xbedbbe16,0xbf67bf7d,0xbeacbf18,0x3f713f4e,0xbf5cbf2c,0xbf04bf3e,0x3e79bd49,0x3f783f80,
0xbf80bf78,0x3d49be79,0x3f3e3f04,0x3f2c3f5c,0xbf4ebf71,0x3f183eac,0x3f7d3f67,0x3e163edb,0x3f553f7b,0xbf0ebe48,0xbf55bf7b,0x3f0e3e48,
0x3e483f0e,0xbf7bbf55,0xbe48bf0e,0x3f7b3f55,0xbf0ebe48,0xbf55bf7b,0x3f0e3e48,0x3f553f7b,0xbf7bbf55,0xbe48bf0e,0x3f7b3f55,0x3e483f0e,
0x3f2c3e79,0x3f3e3f78,0xbf80bf5c,0xbd49bf04,0x3f7d3f71,0xbe163eac,0xbf18bf67,0x3f4e3edb,0x3edb3f4e,0xbf67bf18,0x3eacbe16,0x3f713f7d,
0xbf04bd49,0xbf5cbf80,0x3f783f3e,0x3e793f2c,0xbf22bf75,0x3f463e95,0xbf46be95,0xbf22bf75,0x3ef1bdc9,0x3f623f7f,0xbf62bf7f,0x3ef1bdc9,
0x3f7f3f62,0xbdc93ef1,0x3dc9bef1,0x3f7f3f62,0x3e953f46,0xbf75bf22,0x3f753f22,0x3e953f46,0xbf5cbeac,0xbf04bf71,0xbe793edb,0xbf78bf67,
0xbf2cbf7d,0x3f3e3e16,0xbf80bf4e,0x3d49bf18,0x3f18bd49,0x3f4e3f80,0xbe16bf3e,0x3f7d3f2c,0x3f673f78,0xbedb3e79,0x3f713f04,0x3eac3f5c,
0x3ec43f6d,0xbf6dbec4,0x3ec43f6d,0xbf6dbec4,0xbf6dbec4,0xbec4bf6d,0xbf6dbec4,0xbec4bf6d,0xbec4bf6d,0x3f6d3ec4,0xbec4bf6d,0x3f6d3ec4,
0x3f6d3ec4,0x3ec43f6d,0x3f6d3ec4,0x3ec43f6d,0x3f783edb,0x3e793f67,0x3f5c3f71,0xbf043eac,0x3d493f4e,0xbf80bf18,0xbf2c3e16,0xbf3ebf7d,
0xbf7dbf3e,0x3e16bf2c,0xbf18bf80,0x3f4e3d49,0x3eacbf04,0x3f713f5c,0x3f673e79,0x3edb3f78,0xbdc9bf62,0x3f7f3ef1,0x3f7f3ef1,0x3dc93f62,
0x3f753f46,0xbe953f22,0xbe953f22,0xbf75bf46,0xbf223e95,0xbf46bf75,0xbf46bf75,0x3f22be95,0xbef1bf7f,0x3f623dc9,0x3f623dc9,0x3ef13f7f,
0xbf80bf04,0x3d49bf5c,0x3f3ebe79,0x3f2c3f78,0x3f18bedb,0x3f4e3f67,0x3e163f71,0xbf7dbeac,0x3eac3f7d,0xbf71be16,0xbf67bf4e,0x3edbbf18,
0xbf78bf2c,0x3e79bf3e,0x3f5cbd49,0x3f043f80,0xbe483f55,0xbf7bbf0e,0x3e48bf55,0x3f7b3f0e,0xbf0ebf7b,0x3f55be48,0x3f0e3f7b,0xbf553e48,
0x3f7b3f0e,0xbe483f55,0xbf7bbf0e,0x3e48bf55,0xbf553e48,0xbf0ebf7b,0x3f55be48,0x3f0e3f7b,0x3f713f18,0xbeac3f4e,0xbedbbf7d,0x3f67be16,
0xbf78bd49,0xbe79bf80,0x3f5c3f3e,0xbf043f2c,0x3f2cbf04,0x3f3e3f5c,0xbf80be79,0xbd49bf78,0xbe163f67,0xbf7dbedb,0x3f4ebeac,0x3f183f71,
0x3ef1bf46,0x3f623f22,0xbf62bf22,0x3ef1bf46,0xbdc93f75,0xbf7fbe95,0x3f7f3e95,0xbdc93f75,0xbe95bf7f,0x3f75bdc9,0xbf753dc9,0xbe95bf7f,
0x3f223f62,0xbf463ef1,0x3f46bef1,0x3f223f62,0xbf4ebf2c,0x3f18bf3e,0xbf7d3d49,0xbe16bf80,0x3f673f04,0xbedb3f5c,0x3f71be79,0x3eac3f78,
0xbf78beac,0x3e79bf71,0xbf5c3edb,0xbf04bf67,0x3f803e16,0xbd493f7d,0x3f3ebf18,0x3f2c3f4e,0xbf353f35,0xbf35bf35,0xbf353f35,0xbf35bf35,
0x3f35bf35,0x3f353f35,0x3f35bf35,0x3f353f35,0xbf353f35,0xbf35bf35,0xbf353f35,0xbf35bf35,0x3f35bf35,0x3f353f35,0x3f35bf35,0x3f353f35,
0x3f183f3e,0xbf4e3f2c,0xbe163f80,0xbf7dbd49,0xbedbbf5c,0x3f67bf04,0x3eacbf78,0x3f713e79,0x3e793f71,0xbf783eac,0xbf043f67,0xbf5cbedb,
0xbd49bf7d,0x3f80be16,0x3f2cbf4e,0x3f3e3f18,0x3f62bf22,0x3ef13f46,0x3ef13f46,0xbf623f22,0xbf7f3e95,0xbdc9bf75,0xbdc9bf75,0x3f7fbe95,
0x3f753dc9,0xbe953f7f,0xbe953f7f,0xbf75bdc9,0xbf46bef1,0x3f22bf62,0x3f22bf62,0x3f463ef1,0xbeacbf4e,0x3f71bf18,0x3f673e16,0xbedb3f7d,
0xbe793f80,0xbf783d49,0xbf04bf2c,0x3f5cbf3e,0x3f3ebf5c,0x3f2c3f04,0xbd493f78,0xbf803e79,0xbf7d3edb,0xbe16bf67,0x3f18bf71,0x3f4e3eac,
0xbf7b3f0e,0xbe48bf55,0x3f7bbf0e,0x3e483f55,0x3f553e48,0xbf0e3f7b,0xbf55be48,0x3f0ebf7b,0xbe48bf55,0x3f7bbf0e,0x3e483f55,0xbf7b3f0e,
0xbf0e3f7b,0xbf55be48,0x3f0ebf7b,0x3f553e48,0x3d493f5c,0xbf803f04,0x3f2cbf78,0x3f3e3e79,0x3f4ebf67,0x3f183edb,0xbf7d3eac,0x3e16bf71,
0xbf713e16,0x3eacbf7d,0x3edb3f18,0xbf673f4e,0x3e793f3e,0xbf783f2c,0x3f04bf80,0x3f5c3d49,0x3f7fbef1,0xbdc93f62,0x3dc9bf62,0x3f7fbef1,
0xbe95bf22,0x3f75bf46,0xbf753f46,0xbe95bf22,0xbf463f75,0xbf22be95,0x3f223e95,0xbf463f75,0x3f62bdc9,0xbef13f7f,0x3ef1bf7f,0x3f62bdc9,
0x3e79bf67,0x3f78bedb,0xbf04beac,0x3f5cbf71,0xbf803f18,0x3d49bf4e,0xbf3e3f7d,0xbf2cbe16,0x3e163f2c,0xbf7d3f3e,0x3f4ebd49,0xbf183f80,
0x3f71bf5c,0x3eac3f04,0x3edbbf78,0x3f67be79,0xbf6d3ec4,0x3ec4bf6d,0xbf6d3ec4,0x3ec4bf6d,0xbec43f6d,0xbf6d3ec4,0xbec43f6d,0xbf6d3ec4,
0x3f6dbec4,0xbec43f6d,0x3f6dbec4,0xbec43f6d,0x3ec4bf6d,0x3f6dbec4,0x3ec4bf6d,0x3f6dbec4,0xbf043f71,0xbf5c3eac,0xbf783f67,0xbe79bedb,
0x3f3ebe16,0xbf2c3f7d,0x3d493f18,0xbf803f4e,0x3f4ebf80,0x3f183d49,0x3f7dbf2c,0xbe163f3e,0xbedbbe79,0x3f67bf78,0x3eacbf5c,0x3f71bf04,
0x3f46be95,0xbf223f75,0xbf223f75,0xbf463e95,0x3f62bf7f,0x3ef13dc9,0x3ef13dc9,0xbf623f7f,0xbdc9bef1,0x3f7fbf62,0x3f7fbf62,0x3dc93ef1,
0xbf753f22,0x3e95bf46,0x3e95bf46,0x3f75bf22,0x3f3ebf78,0x3f2cbe79,0xbd493f04,0xbf803f5c,0xbe16beac,0x3f7dbf71,0x3f4ebedb,0xbf183f67,
0xbf673f18,0x3edbbf4e,0x3f71bf7d,0x3eac3e16,0xbf5c3f80,0xbf043d49,0x3e79bf2c,0x3f78bf3e,0xbf0e3e48,0x3f55bf7b,0x3f0ebe48,0xbf553f7b,
0xbf7b3f55,0x3e48bf0e,0x3f7bbf55,0xbe483f0e,0xbf553f7b,0xbf0e3e48,0x3f55bf7b,0x3f0ebe48,0xbe483f0e,0xbf7b3f55,0x3e48bf0e,0x3f7bbf55,
0xbf673f7d,0xbedb3e16,0x3f71bf4e,0xbeac3f18,0xbf043f3e,0xbf5c3f2c,0x3f78bf80,0x3e793d49,0x3d493e79,0xbf803f78,0x3f2cbf5c,0x3f3ebf04,
0x3f18beac,0xbf4e3f71,0x3e16bedb,0x3f7dbf67,0x3e95bdc9,0xbf753f7f,0x3f75bf7f,0x3e95bdc9,0x3f22bef1,0xbf463f62,0x3f46bf62,0x3f22bef1,
0x3f62bf46,0xbef13f22,0x3ef1bf22,0x3f62bf46,0x3f7fbf75,0xbdc93e95,0x3dc9be95,0x3f7fbf75,0x3f7dbf80,0x3e16bd49,0x3f18bf2c,0x3f4ebf3e,
0x3f71bf78,0x3eacbe79,0x3edbbf04,0x3f67bf5c,0x3f5cbf67,0x3f04bedb,0x3e79beac,0x3f78bf71,0x3f3ebf4e,0x3f2cbf18,0x3d49be16,0x3f80bf7d,
0x3f803f80,0xbf353f35,0x3f803f80,0xbf353f35,0x3f803f80,0xbf353f35,0x3f803f80,0xbf353f35,0x3f803f80,0xbf353f35,0x3f803f80,0xbf353f35,
0x3f803f80,0xbf353f35,0x3f803f80,0xbf353f35,0x3f7c3f7f,0xbe2fbd97,0x3f133f27,0xbf51bf42,0x3f6f3f77,0xbeb8be89,0x3ecf3efc,0xbf6abf5f,
0x3f583f65,0xbf09bee6,0x3e603ea1,0xbf7abf73,0x3f393f4a,0xbf31bf1d,0x3cc93dfb,0xbf80bf7e,0x3f713f7d,0xbeacbe16,0xbeacbe16,0xbf71bf7d,
0x3f3e3f5c,0xbf2cbf04,0xbf2cbf04,0xbf3ebf5c,0x3edb3f18,0xbf67bf4e,0xbf67bf4e,0xbedbbf18,0x3d493e79,0xbf80bf78,0xbf80bf78,0xbd49be79,
0x3f5f3f7a,0xbefcbe60,0xbf77bf58,0xbe89bf09,0x3ee63f31,0xbf65bf39,0xbf73bf80,0x3ea13cc9,0xbdfb3e2f,0xbf7ebf7c,0xbf1dbf51,0x3f4a3f13,
0xbf27becf,0xbf42bf6a,0xbd97beb8,0x3f7f3f6f,0x3f463f75,0xbf22be95,0xbf46bf75,0x3f223e95,0x3dc93ef1,0xbf7fbf62,0xbdc9bef1,0x3f7f3f62,
0xbf22be95,0xbf46bf75,0x3f223e95,0x3f463f75,0xbf7fbf62,0xbdc9bef1,0x3f7f3f62,0x3dc93ef1,0x3f273f6f,0xbf42beb8,0x3d97becf,0x3f7f3f6a,
0xbe893e60,0xbf77bf7a,0x3f5f3f09,0x3efc3f58,0xbf73bf31,0xbea1bf39,0x3f653f80,0xbee63cc9,0xbf4abf7c,0x3f1d3e2f,0x3dfb3f13,0xbf7ebf51,
0x3f043f67,0xbf5cbedb,0x3f5c3edb,0x3f043f67,0xbf18bd49,0xbf4ebf80,0x3f4e3f80,0xbf18bd49,0xbf78bf71,0x3e79beac,0xbe793eac,0xbf78bf71,
0xbe16bf2c,0x3f7d3f3e,0xbf7dbf3e,0xbe16bf2c,0x3eb83f5f,0xbf6fbefc,0x3f6a3f77,0xbecf3e89,0xbf58bea1,0xbf09bf73,0xbe603ee6,0xbf7abf65,
0xbf31bf7e,0x3f393dfb,0xbf80bf4a,0x3cc9bf1d,0x3f13bd97,0x3f513f7f,0xbe2fbf42,0x3f7c3f27,0x3e483f55,0xbf7bbf0e,0x3e483f55,0xbf7bbf0e,
0xbf7bbf0e,0xbe48bf55,0xbf7bbf0e,0xbe48bf55,0xbe48bf55,0x3f7b3f0e,0xbe48bf55,0x3f7b3f0e,0x3f7b3f0e,0x3e483f55,0x3f7b3f0e,0x3e483f55,
0x3cc93f4a,0xbf80bf1d,0xbf313dfb,0xbf39bf7e,0xbf7cbf42,0x3e2fbf27,0xbf13bf7f,0x3f513d97,0x3eb8befc,0x3f6f3f5f,0x3f6a3e89,0x3ecf3f77,
0x3f583f73,0xbf093ea1,0x3e603f65,0xbf7abee6,0xbe163f3e,0xbf7dbf2c,0xbf7dbf2c,0x3e16bf3e,0xbf5cbf67,0x3f04bedb,0x3f04bedb,0x3f5c3f67,
0x3f4ebd49,0x3f183f80,0x3f183f80,0xbf4e3d49,0x3e793f71,0xbf78beac,0xbf78beac,0xbe79bf71,0xbea13f31,0xbf73bf39,0xbee6bf80,0x3f653cc9,
0xbf1dbf7c,0x3f4abe2f,0x3f7e3f13,0xbdfb3f51,0x3f7f3ecf,0x3d973f6a,0xbf273eb8,0xbf42bf6f,0xbefc3f09,0xbf5fbf58,0xbe89bf7a,0x3f773e60,
0xbef13f22,0xbf62bf46,0x3ef1bf22,0x3f623f46,0xbe95bf7f,0x3f753dc9,0x3e953f7f,0xbf75bdc9,0x3f623f46,0xbef13f22,0xbf62bf46,0x3ef1bf22,
0xbf75bdc9,0xbe95bf7f,0x3f753dc9,0x3e953f7f,0xbf1d3f13,0xbf4abf51,0x3f7e3e2f,0x3dfb3f7c,0x3d97bf6f,0x3f7f3eb8,0xbf423ecf,0xbf27bf6a,
0x3efc3f7a,0xbf5f3e60,0x3e89bf58,0x3f773f09,0xbf65bf31,0x3ee6bf39,0x3ea13f80,0xbf733cc9,0xbf3e3f04,0xbf2cbf5c,0x3f2c3f5c,0xbf3e3f04,
0x3edbbf4e,0x3f673f18,0xbf67bf18,0x3edbbf4e,0xbd493f78,0xbf80be79,0x3f803e79,0xbd493f78,0xbeacbf7d,0x3f71be16,0xbf713e16,0xbeacbf7d,
0xbf583ee6,0xbf09bf65,0xbe603f73,0xbf7abea1,0x3f39bf1d,0x3f313f4a,0x3cc9bf7e,0x3f803dfb,0xbf133f42,0xbf51bf27,0x3e2f3f7f,0xbf7c3d97,
0x3ecfbf5f,0x3f6a3efc,0xbeb8bf77,0x3f6fbe89,0xbf6d3ec4,0xbec4bf6d,0xbf6d3ec4,0xbec4bf6d,0x3f6dbec4,0x3ec43f6d,0x3f6dbec4,0x3ec43f6d,
0xbf6d3ec4,0xbec4bf6d,0xbf6d3ec4,0xbec4bf6d,0x3f6dbec4,0x3ec43f6d,0x3f6dbec4,0x3ec43f6d,0xbf7a3ea1,0xbe60bf73,0xbf58bee6,0x3f09bf65,
0x3f80bdfb,0x3cc93f7e,0x3f393f1d,0xbf313f4a,0xbf7cbd97,0x3e2fbf7f,0xbf13bf42,0x3f51bf27,0x3f6f3e89,0xbeb83f77,0x3ecf3f5f,0xbf6a3efc,
0xbf803e79,0xbd49bf78,0xbd49bf78,0x3f80be79,0x3f713e16,0xbeac3f7d,0xbeac3f7d,0xbf71be16,0xbf3ebf04,0x3f2cbf5c,0x3f2cbf5c,0x3f3e3f04,
0x3edb3f4e,0xbf673f18,0xbf673f18,0xbedbbf4e,0xbf7e3e2f,0x3dfbbf7c,0x3f4abf51,0x3f1d3f13,0x3f423ecf,0xbf273f6a,0xbf7f3eb8,0xbd97bf6f,
0xbe89bf58,0x3f77bf09,0x3f5f3e60,0xbefc3f7a,0xbea13f80,0xbf73bcc9,0xbee6bf39,0x3f65bf31,0xbf753dc9,0x3e95bf7f,0x3f75bdc9,0xbe953f7f,
0x3ef13f22,0xbf623f46,0xbef1bf22,0x3f62bf46,0x3e95bf7f,0x3f75bdc9,0xbe953f7f,0xbf753dc9,0xbf623f46,0xbef1bf22,0x3f62bf46,0x3ef13f22,
0xbf653cc9,0x3ee6bf80,0x3ea13f31,0xbf733f39,0x3dfb3f51,0xbf7e3f13,0x3f1dbf7c,0x3f4a3e2f,0x3f42bf6f,0x3f273eb8,0xbf7f3ecf,0x3d97bf6a,
0xbf773e60,0x3e89bf7a,0x3efc3f09,0xbf5f3f58,0xbf4ebd49,0x3f18bf80,0xbf183f80,0xbf4ebd49,0xbe793f71,0xbf783eac,0x3f78beac,0xbe793f71,
0x3f7dbf2c,0x3e163f3e,0xbe16bf3e,0x3f7dbf2c,0xbf04bedb,0x3f5cbf67,0xbf5c3f67,0xbf04bedb,0xbf31bdfb,0x3f39bf7e,0xbf803f1d,0x3cc9bf4a,
0xbf133f7f,0xbf513d97,0x3e2f3f27,0xbf7c3f42,0x3f6abe89,0xbecf3f77,0x3f6fbf5f,0x3eb83efc,0x3e60bf65,0x3f7abee6,0xbf09bea1,0x3f58bf73,
0xbf0ebe48,0x3f55bf7b,0xbf0ebe48,0x3f55bf7b,0xbf553f7b,0xbf0ebe48,0xbf553f7b,0xbf0ebe48,0x3f0e3e48,0xbf553f7b,0x3f0e3e48,0xbf553f7b,
0x3f55bf7b,0x3f0e3e48,0x3f55bf7b,0x3f0e3e48,0xbecfbe89,0x3f6abf77,0x3eb8bf5f,0x3f6fbefc,0xbf7a3f65,0xbe60bee6,0xbf583ea1,0x3f09bf73,
0x3cc93f1d,0xbf803f4a,0xbf313f7e,0xbf393dfb,0x3f7cbf27,0xbe2f3f42,0x3f133d97,0xbf513f7f,0xbe79beac,0x3f78bf71,0x3f78bf71,0x3e793eac,
0xbf7d3f3e,0x3e16bf2c,0x3e16bf2c,0x3f7dbf3e,0xbf043f67,0xbf5c3edb,0xbf5c3edb,0x3f04bf67,0x3f18bd49,0xbf4e3f80,0xbf4e3f80,0xbf183d49,
0xbd97becf,0x3f7fbf6a,0x3f42beb8,0xbf273f6f,0xbf5f3f09,0x3efcbf58,0x3f77bf7a,0x3e893e60,0xbf653f80,0xbee6bcc9,0x3ea1bf39,0x3f73bf31,
0xbdfb3f13,0xbf7e3f51,0xbf1d3e2f,0x3f4abf7c,0x3dc9bef1,0x3f7fbf62,0xbdc93ef1,0xbf7f3f62,0xbf223e95,0x3f46bf75,0x3f22be95,0xbf463f75,
0xbf7f3f62,0x3dc9bef1,0x3f7fbf62,0xbdc93ef1,0xbf463f75,0xbf223e95,0x3f46bf75,0x3f22be95,0x3e89bf09,0x3f77bf58,0xbf5f3f7a,0xbefc3e60,
0xbea13cc9,0x3f73bf80,0xbee63f31,0xbf653f39,0xbf4a3f13,0x3f1dbf51,0x3dfb3e2f,0xbf7e3f7c,0xbf7f3f6f,0x3d97beb8,0x3f27becf,0xbf423f6a,
0x3edbbf18,0x3f67bf4e,0xbf673f4e,0x3edbbf18,0x3d49be79,0x3f80bf78,0xbf803f78,0x3d49be79,0xbeac3e16,0x3f71bf7d,0xbf713f7d,0xbeac3e16,
0xbf2c3f04,0x3f3ebf5c,0xbf3e3f5c,0xbf2c3f04,0x3f13bf27,0x3f51bf42,0xbe2f3d97,0x3f7cbf7f,0x3ecfbefc,0x3f6abf5f,0xbeb83e89,0x3f6fbf77,
0x3e60bea1,0x3f7abf73,0xbf093ee6,0x3f58bf65,0x3cc9bdfb,0x3f80bf7e,0xbf313f1d,0x3f39bf4a,0x3f803f80,0xbf353f35,0x3f803f80,0xbf353f35,
0x3f803f80,0xbf353f35,0x3f803f80,0xbf353f35,0x3f803f80,0xbf353f35,0x3f803f80,0xbf353f35,0x3f803f80,0xbf353f35,0x3f803f80,0xbf353f35,
0xbe2fbd97,0xbf7cbf7f,0xbf51bf42,0xbf13bf27,0xbeb8be89,0xbf6fbf77,0xbf6abf5f,0xbecfbefc,0xbf09bee6,0xbf58bf65,0xbf7abf73,0xbe60bea1,
0xbf31bf1d,0xbf39bf4a,0xbf80bf7e,0xbcc9bdfb,0xbf71bf7d,0x3eac3e16,0x3eac3e16,0x3f713f7d,0xbf3ebf5c,0x3f2c3f04,0x3f2c3f04,0x3f3e3f5c,
0xbedbbf18,0x3f673f4e,0x3f673f4e,0x3edb3f18,0xbd49be79,0x3f803f78,0x3f803f78,0x3d493e79,0x3efc3e60,0x3f5f3f7a,0x3e893f09,0xbf77bf58,
0x3f653f39,0x3ee63f31,0xbea1bcc9,0xbf73bf80,0x3f7e3f7c,0xbdfb3e2f,0xbf4abf13,0xbf1dbf51,0x3f423f6a,0xbf27becf,0xbf7fbf6f,0xbd97beb8,
0x3f463f75,0xbf22be95,0xbf46bf75,0x3f223e95,0x3dc93ef1,0xbf7fbf62,0xbdc9bef1,0x3f7f3f62,0xbf22be95,0xbf46bf75,0x3f223e95,0x3f463f75,
0xbf7fbf62,0xbdc9bef1,0x3f7f3f62,0x3dc93ef1,0xbf42beb8,0xbf27bf6f,0x3f7f3f6a,0xbd973ecf,0xbf77bf7a,0x3e89be60,0x3efc3f58,0xbf5fbf09,
0xbea1bf39,0x3f733f31,0xbee63cc9,0xbf65bf80,0x3f1d3e2f,0x3f4a3f7c,0xbf7ebf51,0xbdfbbf13,0xbf04bf67,0x3f5c3edb,0xbf5cbedb,0xbf04bf67,
0x3f183d49,0x3f4e3f80,0xbf4ebf80,0x3f183d49,0x3f783f71,0xbe793eac,0x3e79beac,0x3f783f71,0x3e163f2c,0xbf7dbf3e,0x3f7d3f3e,0x3e163f2c,
0x3f6f3efc,0x3eb83f5f,0x3ecfbe89,0x3f6a3f77,0x3f093f73,0xbf58bea1,0x3f7a3f65,0xbe603ee6,0xbf39bdfb,0xbf31bf7e,0xbcc93f1d,0xbf80bf4a,
0xbf51bf7f,0x3f13bd97,0xbf7cbf27,0xbe2fbf42,0x3e483f55,0xbf7bbf0e,0x3e483f55,0xbf7bbf0e,0xbf7bbf0e,0xbe48bf55,0xbf7bbf0e,0xbe48bf55,
0xbe48bf55,0x3f7b3f0e,0xbe48bf55,0x3f7b3f0e,0x3f7b3f0e,0x3e483f55,0x3f7b3f0e,0x3e483f55,0xbf80bf1d,0xbcc9bf4a,0xbf39bf7e,0x3f31bdfb,
0x3e2fbf27,0x3f7c3f42,0x3f513d97,0x3f133f7f,0x3f6f3f5f,0xbeb83efc,0x3ecf3f77,0xbf6abe89,0xbf093ea1,0xbf58bf73,0xbf7abee6,0xbe60bf65,
0x3e16bf3e,0x3f7d3f2c,0x3f7d3f2c,0xbe163f3e,0x3f5c3f67,0xbf043edb,0xbf043edb,0xbf5cbf67,0xbf4e3d49,0xbf18bf80,0xbf18bf80,0x3f4ebd49,
0xbe79bf71,0x3f783eac,0x3f783eac,0x3e793f71,0x3f733f39,0xbea13f31,0xbf65bcc9,0xbee6bf80,0xbf4a3e2f,0xbf1dbf7c,0x3dfbbf51,0x3f7e3f13,
0xbd97bf6a,0x3f7f3ecf,0x3f423f6f,0xbf273eb8,0x3f5f3f58,0xbefc3f09,0xbf77be60,0xbe89bf7a,0xbef13f22,0xbf62bf46,0x3ef1bf22,0x3f623f46,
0xbe95bf7f,0x3f753dc9,0x3e953f7f,0xbf75bdc9,0x3f623f46,0xbef13f22,0xbf62bf46,0x3ef1bf22,0xbf75bdc9,0xbe95bf7f,0x3f753dc9,0x3e953f7f,
0xbf4abf51,0x3f1dbf13,0x3dfb3f7c,0xbf7ebe2f,0x3f7f3eb8,0xbd973f6f,0xbf27bf6a,0x3f42becf,0xbf5f3e60,0xbefcbf7a,0x3f773f09,0xbe893f58,
0x3ee6bf39,0x3f653f31,0xbf733cc9,0xbea1bf80,0x3f3ebf04,0x3f2c3f5c,0xbf2cbf5c,0x3f3ebf04,0xbedb3f4e,0xbf67bf18,0x3f673f18,0xbedb3f4e,
0x3d49bf78,0x3f803e79,0xbf80be79,0x3d49bf78,0x3eac3f7d,0xbf713e16,0x3f71be16,0x3eac3f7d,0x3f093f65,0xbf583ee6,0x3f7a3ea1,0xbe603f73,
0xbf31bf4a,0x3f39bf1d,0xbf80bdfb,0x3cc9bf7e,0x3f513f27,0xbf133f42,0x3f7cbd97,0x3e2f3f7f,0xbf6abefc,0x3ecfbf5f,0xbf6f3e89,0xbeb8bf77,
0xbf6d3ec4,0xbec4bf6d,0xbf6d3ec4,0xbec4bf6d,0x3f6dbec4,0x3ec43f6d,0x3f6dbec4,0x3ec43f6d,0xbf6d3ec4,0xbec4bf6d,0xbf6d3ec4,0xbec4bf6d,
0x3f6dbec4,0x3ec43f6d,0x3f6dbec4,0x3ec43f6d,0xbe60bf73,0x3f7abea1,0x3f09bf65,0x3f583ee6,0x3cc93f7e,0xbf803dfb,0xbf313f4a,0xbf39bf1d,
0x3e2fbf7f,0x3f7c3d97,0x3f51bf27,0x3f133f42,0xbeb83f77,0xbf6fbe89,0xbf6a3efc,0xbecfbf5f,0x3f80be79,0x3d493f78,0x3d493f78,0xbf803e79,
0xbf71be16,0x3eacbf7d,0x3eacbf7d,0x3f713e16,0x3f3e3f04,0xbf2c3f5c,0xbf2c3f5c,0xbf3ebf04,0xbedbbf4e,0x3f67bf18,0x3f67bf18,0x3edb3f4e,
0xbdfb3f7c,0xbf7e3e2f,0xbf1dbf13,0x3f4abf51,0x3f27bf6a,0x3f423ecf,0x3d973f6f,0xbf7f3eb8,0xbf773f09,0xbe89bf58,0x3efcbf7a,0x3f5f3e60,
0x3f733cc9,0xbea13f80,0xbf653f31,0xbee6bf39,0xbf753dc9,0x3e95bf7f,0x3f75bdc9,0xbe953f7f,0x3ef13f22,0xbf623f46,0xbef1bf22,0x3f62bf46,
0x3e95bf7f,0x3f75bdc9,0xbe953f7f,0xbf753dc9,0xbf623f46,0xbef1bf22,0x3f62bf46,0x3ef13f22,0x3ee6bf80,0x3f65bcc9,0xbf733f39,0xbea1bf31,
0xbf7e3f13,0xbdfbbf51,0x3f4a3e2f,0xbf1d3f7c,0x3f273eb8,0xbf423f6f,0x3d97bf6a,0x3f7fbecf,0x3e89bf7a,0x3f77be60,0xbf5f3f58,0xbefcbf09,
0x3f4e3d49,0xbf183f80,0x3f18bf80,0x3f4e3d49,0x3e79bf71,0x3f78beac,0xbf783eac,0x3e79bf71,0xbf7d3f2c,0xbe16bf3e,0x3e163f3e,0xbf7d3f2c,
0x3f043edb,0xbf5c3f67,0x3f5cbf67,0x3f043edb,0xbf393f7e,0xbf31bdfb,0xbcc93f4a,0xbf803f1d,0x3f51bd97,0xbf133f7f,0x3f7cbf42,0x3e2f3f27,
0x3ecfbf77,0x3f6abe89,0xbeb8befc,0x3f6fbf5f,0xbf7a3ee6,0x3e60bf65,0xbf583f73,0xbf09bea1,0xbf0ebe48,0x3f55bf7b,0xbf0ebe48,0x3f55bf7b,
0xbf553f7b,0xbf0ebe48,0xbf553f7b,0xbf0ebe48,0x3f0e3e48,0xbf553f7b,0x3f0e3e48,0xbf553f7b,0x3f55bf7b,0x3f0e3e48,0x3f55bf7b,0x3f0e3e48,
0x3f6abf77,0x3ecf3e89,0x3f6fbefc,0xbeb83f5f,0xbe60bee6,0x3f7abf65,0x3f09bf73,0x3f58bea1,0xbf803f4a,0xbcc9bf1d,0xbf393dfb,0x3f31bf7e,
0xbe2f3f42,0xbf7c3f27,0xbf513f7f,0xbf13bd97,0x3e793eac,0xbf783f71,0xbf783f71,0xbe79beac,0x3f7dbf3e,0xbe163f2c,0xbe163f2c,0xbf7d3f3e,
0x3f04bf67,0x3f5cbedb,0x3f5cbedb,0xbf043f67,0xbf183d49,0x3f4ebf80,0x3f4ebf80,0x3f18bd49,0xbf7f3f6a,0xbd97becf,0x3f27bf6f,0x3f42beb8,
0xbefc3f58,0xbf5f3f09,0xbe89be60,0x3f77bf7a,0x3ee63cc9,0xbf653f80,0xbf733f31,0x3ea1bf39,0x3f7ebf51,0xbdfb3f13,0xbf4a3f7c,0xbf1d3e2f,
0x3dc9bef1,0x3f7fbf62,0xbdc93ef1,0xbf7f3f62,0xbf223e95,0x3f46bf75,0x3f22be95,0xbf463f75,0xbf7f3f62,0x3dc9bef1,0x3f7fbf62,0xbdc93ef1,
0xbf463f75,0xbf223e95,0x3f46bf75,0x3f22be95,0x3f77bf58,0xbe893f09,0xbefc3e60,0x3f5fbf7a,0x3f73bf80,0x3ea1bcc9,0xbf653f39,0x3ee6bf31,
0x3f1dbf51,0x3f4abf13,0xbf7e3f7c,0xbdfbbe2f,0x3d97beb8,0x3f7fbf6f,0xbf423f6a,0xbf273ecf,0xbedb3f18,0xbf673f4e,0x3f67bf4e,0xbedb3f18,
0xbd493e79,0xbf803f78,0x3f80bf78,0xbd493e79,0x3eacbe16,0xbf713f7d,0x3f71bf7d,0x3eacbe16,0x3f2cbf04,0xbf3e3f5c,0x3f3ebf5c,0x3f2cbf04,
0xbf513f42,0x3f13bf27,0xbf7c3f7f,0xbe2f3d97,0xbf6a3f5f,0x3ecfbefc,0xbf6f3f77,0xbeb83e89,0xbf7a3f73,0x3e60bea1,0xbf583f65,0xbf093ee6,
0xbf803f7e,0x3cc9bdfb,0xbf393f4a,0xbf313f1d,0x3f803f80,0xbf353f35,0x3f803f80,0xbf353f35,0x3f803f80,0xbf353f35,0x3f803f80,0xbf353f35,
0x3f803f80,0xbf353f35,0x3f803f80,0xbf353f35,0x3f803f80,0xbf353f35,0x3f803f80,0xbf353f35,0xbf7cbf7f,0x3e2f3d97,0xbf13bf27,0x3f513f42,
0xbf6fbf77,0x3eb83e89,0xbecfbefc,0x3f6a3f5f,0xbf58bf65,0x3f093ee6,0xbe60bea1,0x3f7a3f73,0xbf39bf4a,0x3f313f1d,0xbcc9bdfb,0x3f803f7e,
0x3f713f7d,0xbeacbe16,0xbeacbe16,0xbf71bf7d,0x3f3e3f5c,0xbf2cbf04,0xbf2cbf04,0xbf3ebf5c,0x3edb3f18,0xbf67bf4e,0xbf67bf4e,0xbedbbf18,
0x3d493e79,0xbf80bf78,0xbf80bf78,0xbd49be79,0xbf5fbf7a,0x3efc3e60,0x3f773f58,0x3e893f09,0xbee6bf31,0x3f653f39,0x3f733f80,0xbea1bcc9,
0x3dfbbe2f,0x3f7e3f7c,0x3f1d3f51,0xbf4abf13,0x3f273ecf,0x3f423f6a,0x3d973eb8,0xbf7fbf6f,0x3f463f75,0xbf22be95,0xbf46bf75,0x3f223e95,
0x3dc93ef1,0xbf7fbf62,0xbdc9bef1,0x3f7f3f62,0xbf22be95,0xbf46bf75,0x3f223e95,0x3f463f75,0xbf7fbf62,0xbdc9bef1,0x3f7f3f62,0x3dc93ef1,
0xbf27bf6f,0x3f423eb8,0xbd973ecf,0xbf7fbf6a,0x3e89be60,0x3f773f7a,0xbf5fbf09,0xbefcbf58,0x3f733f31,0x3ea13f39,0xbf65bf80,0x3ee6bcc9,
0x3f4a3f7c,0xbf1dbe2f,0xbdfbbf13,0x3f7e3f51,0x3f043f67,0xbf5cbedb,0x3f5c3edb,0x3f043f67,0xbf18bd49,0xbf4ebf80,0x3f4e3f80,0xbf18bd49,
0xbf78bf71,0x3e79beac,0xbe793eac,0xbf78bf71,0xbe16bf2c,0x3f7d3f3e,0xbf7dbf3e,0xbe16bf2c,0xbeb8bf5f,0x3f6f3efc,0xbf6abf77,0x3ecfbe89,
0x3f583ea1,0x3f093f73,0x3e60bee6,0x3f7a3f65,0x3f313f7e,0xbf39bdfb,0x3f803f4a,0xbcc93f1d,0xbf133d97,0xbf51bf7f,0x3e2f3f42,0xbf7cbf27,
0x3e483f55,0xbf7bbf0e,0x3e483f55,0xbf7bbf0e,0xbf7bbf0e,0xbe48bf55,0xbf7bbf0e,0xbe48bf55,0xbe48bf55,0x3f7b3f0e,0xbe48bf55,0x3f7b3f0e,
0x3f7b3f0e,0x3e483f55,0x3f7b3f0e,0x3e483f55,0xbcc9bf4a,0x3f803f1d,0x3f31bdfb,0x3f393f7e,0x3f7c3f42,0xbe2f3f27,0x3f133f7f,0xbf51bd97,
0xbeb83efc,0xbf6fbf5f,0xbf6abe89,0xbecfbf77,0xbf58bf73,0x3f09bea1,0xbe60bf65,0x3f7a3ee6,0xbe163f3e,0xbf7dbf2c,0xbf7dbf2c,0x3e16bf3e,
0xbf5cbf67,0x3f04bedb,0x3f04bedb,0x3f5c3f67,0x3f4ebd49,0x3f183f80,0x3f183f80,0xbf4e3d49,0x3e793f71,0xbf78beac,0xbf78beac,0xbe79bf71,
0x3ea1bf31,0x3f733f39,0x3ee63f80,0xbf65bcc9,0x3f1d3f7c,0xbf4a3e2f,0xbf7ebf13,0x3dfbbf51,0xbf7fbecf,0xbd97bf6a,0x3f27beb8,0x3f423f6f,
0x3efcbf09,0x3f5f3f58,0x3e893f7a,0xbf77be60,0xbef13f22,0xbf62bf46,0x3ef1bf22,0x3f623f46,0xbe95bf7f,0x3f753dc9,0x3e953f7f,0xbf75bdc9,
0x3f623f46,0xbef13f22,0xbf62bf46,0x3ef1bf22,0xbf75bdc9,0xbe95bf7f,0x3f753dc9,0x3e953f7f,0x3f1dbf13,0x3f4a3f51,0xbf7ebe2f,0xbdfbbf7c,
0xbd973f6f,0xbf7fbeb8,0x3f42becf,0x3f273f6a,0xbefcbf7a,0x3f5fbe60,0xbe893f58,0xbf77bf09,0x3f653f31,0xbee63f39,0xbea1bf80,0x3f73bcc9,
0xbf3e3f04,0xbf2cbf5c,0x3f2c3f5c,0xbf3e3f04,0x3edbbf4e,0x3f673f18,0xbf67bf18,0x3edbbf4e,0xbd493f78,0xbf80be79,0x3f803e79,0xbd493f78,
0xbeacbf7d,0x3f71be16,0xbf713e16,0xbeacbf7d,0x3f58bee6,0x3f093f65,0x3e60bf73,0x3f7a3ea1,0xbf393f1d,0xbf31bf4a,0xbcc93f7e,0xbf80bdfb,
0x3f13bf42,0x3f513f27,0xbe2fbf7f,0x3f7cbd97,0xbecf3f5f,0xbf6abefc,0x3eb83f77,0xbf6f3e89,0xbf6d3ec4,0xbec4bf6d,0xbf6d3ec4,0xbec4bf6d,
0x3f6dbec4,0x3ec43f6d,0x3f6dbec4,0x3ec43f6d,0xbf6d3ec4,0xbec4bf6d,0xbf6d3ec4,0xbec4bf6d,0x3f6dbec4,0x3ec43f6d,0x3f6dbec4,0x3ec43f6d,
0x3f7abea1,0x3e603f73,0x3f583ee6,0xbf093f65,0xbf803dfb,0xbcc9bf7e,0xbf39bf1d,0x3f31bf4a,0x3f7c3d97,0xbe2f3f7f,0x3f133f42,0xbf513f27,
0xbf6fbe89,0x3eb8bf77,0xbecfbf5f,0x3f6abefc,0xbf803e79,0xbd49bf78,0xbd49bf78,0x3f80be79,0x3f713e16,0xbeac3f7d,0xbeac3f7d,0xbf71be16,
0xbf3ebf04,0x3f2cbf5c,0x3f2cbf5c,0x3f3e3f04,0x3edb3f4e,0xbf673f18,0xbf673f18,0xbedbbf4e,0x3f7ebe2f,0xbdfb3f7c,0xbf4a3f51,0xbf1dbf13,
0xbf42becf,0x3f27bf6a,0x3f7fbeb8,0x3d973f6f,0x3e893f58,0xbf773f09,0xbf5fbe60,0x3efcbf7a,0x3ea1bf80,0x3f733cc9,0x3ee63f39,0xbf653f31,
0xbf753dc9,0x3e95bf7f,0x3f75bdc9,0xbe953f7f,0x3ef13f22,0xbf623f46,0xbef1bf22,0x3f62bf46,0x3e95bf7f,0x3f75bdc9,0xbe953f7f,0xbf753dc9,
0xbf623f46,0xbef1bf22,0x3f62bf46,0x3ef13f22,0x3f65bcc9,0xbee63f80,0xbea1bf31,0x3f73bf39,0xbdfbbf51,0x3f7ebf13,0xbf1d3f7c,0xbf4abe2f,
0xbf423f6f,0xbf27beb8,0x3f7fbecf,0xbd973f6a,0x3f77be60,0xbe893f7a,0xbefcbf09,0x3f5fbf58,0xbf4ebd49,0x3f18bf80,0xbf183f80,0xbf4ebd49,
0xbe793f71,0xbf783eac,0x3f78beac,0xbe793f71,0x3f7dbf2c,0x3e163f3e,0xbe16bf3e,0x3f7dbf2c,0xbf04bedb,0x3f5cbf67,0xbf5c3f67,0xbf04bedb,
0x3f313dfb,0xbf393f7e,0x3f80bf1d,0xbcc93f4a,0x3f13bf7f,0x3f51bd97,0xbe2fbf27,0x3f7cbf42,0xbf6a3e89,0x3ecfbf77,0xbf6f3f5f,0xbeb8befc,
0xbe603f65,0xbf7a3ee6,0x3f093ea1,0xbf583f73,0xbf0ebe48,0x3f55bf7b,0xbf0ebe48,0x3f55bf7b,0xbf553f7b,0xbf0ebe48,0xbf553f7b,0xbf0ebe48,
0x3f0e3e48,0xbf553f7b,0x3f0e3e48,0xbf553f7b,0x3f55bf7b,0x3f0e3e48,0x3f55bf7b,0x3f0e3e48,0x3ecf3e89,0xbf6a3f77,0xbeb83f5f,0xbf6f3efc,
0x3f7abf65,0x3e603ee6,0x3f58bea1,0xbf093f73,0xbcc9bf1d,0x3f80bf4a,0x3f31bf7e,0x3f39bdfb,0xbf7c3f27,0x3e2fbf42,0xbf13bd97,0x3f51bf7f,
0xbe79beac,0x3f78bf71,0x3f78bf71,0x3e793eac,0xbf7d3f3e,0x3e16bf2c,0x3e16bf2c,0x3f7dbf3e,0xbf043f67,0xbf5c3edb,0xbf5c3edb,0x3f04bf67,
0x3f18bd49,0xbf4e3f80,0xbf4e3f80,0xbf183d49,0x3d973ecf,0xbf7f3f6a,0xbf423eb8,0x3f27bf6f,0x3f5fbf09,0xbefc3f58,0xbf773f7a,0xbe89be60,
0x3f65bf80,0x3ee63cc9,0xbea13f39,0xbf733f31,0x3dfbbf13,0x3f7ebf51,0x3f1dbe2f,0xbf4a3f7c,0x3dc9bef1,0x3f7fbf62,0xbdc93ef1,0xbf7f3f62,
0xbf223e95,0x3f46bf75,0x3f22be95,0xbf463f75,0xbf7f3f62,0x3dc9bef1,0x3f7fbf62,0xbdc93ef1,0xbf463f75,0xbf223e95,0x3f46bf75,0x3f22be95,
0xbe893f09,0xbf773f58,0x3f5fbf7a,0x3efcbe60,0x3ea1bcc9,0xbf733f80,0x3ee6bf31,0x3f65bf39,0x3f4abf13,0xbf1d3f51,0xbdfbbe2f,0x3f7ebf7c,
0x3f7fbf6f,0xbd973eb8,0xbf273ecf,0x3f42bf6a,0x3edbbf18,0x3f67bf4e,0xbf673f4e,0x3edbbf18,0x3d49be79,0x3f80bf78,0xbf803f78,0x3d49be79,
0xbeac3e16,0x3f71bf7d,0xbf713f7d,0xbeac3e16,0xbf2c3f04,0x3f3ebf5c,0xbf3e3f5c,0xbf2c3f04,0xbf133f27,0xbf513f42,0x3e2fbd97,0xbf7c3f7f,
0xbecf3efc,0xbf6a3f5f,0x3eb8be89,0xbf6f3f77,0xbe603ea1,0xbf7a3f73,0x3f09bee6,0xbf583f65,0xbcc93dfb,0xbf803f7e,0x3f31bf1d,0xbf393f4a,
0x3f803f80,0xbf353f35,0x3f803f80,0xbf353f35,0x3f803f80,0xbf353f35,0x3f803f80,0xbf353f35,0x3f803f80,0xbf353f35,0x3f803f80,0xbf353f35,
0x3f803f80,0xbf353f35,0x3f803f80,0xbf353f35,0x3e2f3d97,0x3f7c3f7f,0x3f513f42,0x3f133f27,0x3eb83e89,0x3f6f3f77,0x3f6a3f5f,0x3ecf3efc,
0x3f093ee6,0x3f583f65,0x3f7a3f73,0x3e603ea1,0x3f313f1d,0x3f393f4a,0x3f803f7e,0x3cc93dfb,0xbf71bf7d,0x3eac3e16,0x3eac3e16,0x3f713f7d,
0xbf3ebf5c,0x3f2c3f04,0x3f2c3f04,0x3f3e3f5c,0xbedbbf18,0x3f673f4e,0x3f673f4e,0x3edb3f18,0xbd49be79,0x3f803f78,0x3f803f78,0x3d493e79,
0xbefcbe60,0xbf5fbf7a,0xbe89bf09,0x3f773f58,0xbf65bf39,0xbee6bf31,0x3ea13cc9,0x3f733f80,0xbf7ebf7c,0x3dfbbe2f,0x3f4a3f13,0x3f1d3f51,
0xbf42bf6a,0x3f273ecf,0x3f7f3f6f,0x3d973eb8,0x3f463f75,0xbf22be95,0xbf46bf75,0x3f223e95,0x3dc93ef1,0xbf7fbf62,0xbdc9bef1,0x3f7f3f62,
0xbf22be95,0xbf46bf75,0x3f223e95,0x3f463f75,0xbf7fbf62,0xbdc9bef1,0x3f7f3f62,0x3dc93ef1,0x3f423eb8,0x3f273f6f,0xbf7fbf6a,0x3d97becf,
0x3f773f7a,0xbe893e60,0xbefcbf58,0x3f5f3f09,0x3ea13f39,0xbf73bf31,0x3ee6bcc9,0x3f653f80,0xbf1dbe2f,0xbf4abf7c,0x3f7e3f51,0x3dfb3f13,
0xbf04bf67,0x3f5c3edb,0xbf5cbedb,0xbf04bf67,0x3f183d49,0x3f4e3f80,0xbf4ebf80,0x3f183d49,0x3f783f71,0xbe793eac,0x3e79beac,0x3f783f71,
0x3e163f2c,0xbf7dbf3e,0x3f7d3f3e,0x3e163f2c,0xbf6fbefc,0xbeb8bf5f,0xbecf3e89,0xbf6abf77,0xbf09bf73,0x3f583ea1,0xbf7abf65,0x3e60bee6,
0x3f393dfb,0x3f313f7e,0x3cc9bf1d,0x3f803f4a,0x3f513f7f,0xbf133d97,0x3f7c3f27,0x3e2f3f42,0x3e483f55,0xbf7bbf0e,0x3e483f55,0xbf7bbf0e,
0xbf7bbf0e,0xbe48bf55,0xbf7bbf0e,0xbe48bf55,0xbe48bf55,0x3f7b3f0e,0xbe48bf55,0x3f7b3f0e,0x3f7b3f0e,0x3e483f55,0x3f7b3f0e,0x3e483f55,
0x3f803f1d,0x3cc93f4a,0x3f393f7e,0xbf313dfb,0xbe2f3f27,0xbf7cbf42,0xbf51bd97,0xbf13bf7f,0xbf6fbf5f,0x3eb8befc,0xbecfbf77,0x3f6a3e89,
0x3f09bea1,0x3f583f73,0x3f7a3ee6,0x3e603f65,0x3e16bf3e,0x3f7d3f2c,0x3f7d3f2c,0xbe163f3e,0x3f5c3f67,0xbf043edb,0xbf043edb,0xbf5cbf67,
0xbf4e3d49,0xbf18bf80,0xbf18bf80,0x3f4ebd49,0xbe79bf71,0x3f783eac,0x3f783eac,0x3e793f71,0xbf73bf39,0x3ea1bf31,0x3f653cc9,0x3ee63f80,
0x3f4abe2f,0x3f1d3f7c,0xbdfb3f51,0xbf7ebf13,0x3d973f6a,0xbf7fbecf,0xbf42bf6f,0x3f27beb8,0xbf5fbf58,0x3efcbf09,0x3f773e60,0x3e893f7a,
0xbef13f22,0xbf62bf46,0x3ef1bf22,0x3f623f46,0xbe95bf7f,0x3f753dc9,0x3e953f7f,0xbf75bdc9,0x3f623f46,0xbef13f22,0xbf62bf46,0x3ef1bf22,
0xbf75bdc9,0xbe95bf7f,0x3f753dc9,0x3e953f7f,0x3f4a3f51,0xbf1d3f13,0xbdfbbf7c,0x3f7e3e2f,0xbf7fbeb8,0x3d97bf6f,0x3f273f6a,0xbf423ecf,
0x3f5fbe60,0x3efc3f7a,0xbf77bf09,0x3e89bf58,0xbee63f39,0xbf65bf31,0x3f73bcc9,0x3ea13f80,0x3f3ebf04,0x3f2c3f5c,0xbf2cbf5c,0x3f3ebf04,
0xbedb3f4e,0xbf67bf18,0x3f673f18,0xbedb3f4e,0x3d49bf78,0x3f803e79,0xbf80be79,0x3d49bf78,0x3eac3f7d,0xbf713e16,0x3f71be16,0x3eac3f7d,
0xbf09bf65,0x3f58bee6,0xbf7abea1,0x3e60bf73,0x3f313f4a,0xbf393f1d,0x3f803dfb,0xbcc93f7e,0xbf51bf27,0x3f13bf42,0xbf7c3d97,0xbe2fbf7f,
0x3f6a3efc,0xbecf3f5f,0x3f6fbe89,0x3eb83f77,0xbf6d3ec4,0xbec4bf6d,0xbf6d3ec4,0xbec4bf6d,0x3f6dbec4,0x3ec43f6d,0x3f6dbec4,0x3ec43f6d,
0xbf6d3ec4,0xbec4bf6d,0xbf6d3ec4,0xbec4bf6d,0x3f6dbec4,0x3ec43f6d,0x3f6dbec4,0x3ec43f6d,0x3e603f73,0xbf7a3ea1,0xbf093f65,0xbf58bee6,
0xbcc9bf7e,0x3f80bdfb,0x3f31bf4a,0x3f393f1d,0xbe2f3f7f,0xbf7cbd97,0xbf513f27,0xbf13bf42,0x3eb8bf77,0x3f6f3e89,0x3f6abefc,0x3ecf3f5f,
0x3f80be79,0x3d493f78,0x3d493f78,0xbf803e79,0xbf71be16,0x3eacbf7d,0x3eacbf7d,0x3f713e16,0x3f3e3f04,0xbf2c3f5c,0xbf2c3f5c,0xbf3ebf04,
0xbedbbf4e,0x3f67bf18,0x3f67bf18,0x3edb3f4e,0x3dfbbf7c,0x3f7ebe2f,0x3f1d3f13,0xbf4a3f51,0xbf273f6a,0xbf42becf,0xbd97bf6f,0x3f7fbeb8,
0x3f77bf09,0x3e893f58,0xbefc3f7a,0xbf5fbe60,0xbf73bcc9,0x3ea1bf80,0x3f65bf31,0x3ee63f39,0xbf753dc9,0x3e95bf7f,0x3f75bdc9,0xbe953f7f,
0x3ef13f22,0xbf623f46,0xbef1bf22,0x3f62bf46,0x3e95bf7f,0x3f75bdc9,0xbe953f7f,0xbf753dc9,0xbf623f46,0xbef1bf22,0x3f62bf46,0x3ef13f22,
0xbee63f80,0xbf653cc9,0x3f73bf39,0x3ea13f31,0x3f7ebf13,0x3dfb3f51,0xbf4abe2f,0x3f1dbf7c,0xbf27beb8,0x3f42bf6f,0xbd973f6a,0xbf7f3ecf,
0xbe893f7a,0xbf773e60,0x3f5fbf58,0x3efc3f09,0x3f4e3d49,0xbf183f80,0x3f18bf80,0x3f4e3d49,0x3e79bf71,0x3f78beac,0xbf783eac,0x3e79bf71,
0xbf7d3f2c,0xbe16bf3e,0x3e163f3e,0xbf7d3f2c,0x3f043edb,0xbf5c3f67,0x3f5cbf67,0x3f043edb,0x3f39bf7e,0x3f313dfb,0x3cc9bf4a,0x3f80bf1d,
0xbf513d97,0x3f13bf7f,0xbf7c3f42,0xbe2fbf27,0xbecf3f77,0xbf6a3e89,0x3eb83efc,0xbf6f3f5f,0x3f7abee6,0xbe603f65,0x3f58bf73,0x3f093ea1,
0xbf0ebe48,0x3f55bf7b,0xbf0ebe48,0x3f55bf7b,0xbf553f7b,0xbf0ebe48,0xbf553f7b,0xbf0ebe48,0x3f0e3e48,0xbf553f7b,0x3f0e3e48,0xbf553f7b,
0x3f55bf7b,0x3f0e3e48,0x3f55bf7b,0x3f0e3e48,0xbf6a3f77,0xbecfbe89,0xbf6f3efc,0x3eb8bf5f,0x3e603ee6,0xbf7a3f65,0xbf093f73,0xbf583ea1,
0x3f80bf4a,0x3cc93f1d,0x3f39bdfb,0xbf313f7e,0x3e2fbf42,0x3f7cbf27,0x3f51bf7f,0x3f133d97,0x3e793eac,0xbf783f71,0xbf783f71,0xbe79beac,
0x3f7dbf3e,0xbe163f2c,0xbe163f2c,0xbf7d3f3e,0x3f04bf67,0x3f5cbedb,0x3f5cbedb,0xbf043f67,0xbf183d49,0x3f4ebf80,0x3f4ebf80,0x3f18bd49,
0x3f7fbf6a,0x3d973ecf,0xbf273f6f,0xbf423eb8,0x3efcbf58,0x3f5fbf09,0x3e893e60,0xbf773f7a,0xbee6bcc9,0x3f65bf80,0x3f73bf31,0xbea13f39,
0xbf7e3f51,0x3dfbbf13,0x3f4abf7c,0x3f1dbe2f,0x3dc9bef1,0x3f7fbf62,0xbdc93ef1,0xbf7f3f62,0xbf223e95,0x3f46bf75,0x3f22be95,0xbf463f75,
0xbf7f3f62,0x3dc9bef1,0x3f7fbf62,0xbdc93ef1,0xbf463f75,0xbf223e95,0x3f46bf75,0x3f22be95,0xbf773f58,0x3e89bf09,0x3efcbe60,0xbf5f3f7a,
0xbf733f80,0xbea13cc9,0x3f65bf39,0xbee63f31,0xbf1d3f51,0xbf4a3f13,0x3f7ebf7c,0x3dfb3e2f,0xbd973eb8,0xbf7f3f6f,0x3f42bf6a,0x3f27becf,
0xbedb3f18,0xbf673f4e,0x3f67bf4e,0xbedb3f18,0xbd493e79,0xbf803f78,0x3f80bf78,0xbd493e79,0x3eacbe16,0xbf713f7d,0x3f71bf7d,0x3eacbe16,
0x3f2cbf04,0xbf3e3f5c,0x3f3ebf5c,0x3f2cbf04,0x3f51bf42,0xbf133f27,0x3f7cbf7f,0x3e2fbd97,0x3f6abf5f,0xbecf3efc,0x3f6fbf77,0x3eb8be89,
0x3f7abf73,0xbe603ea1,0x3f58bf65,0x3f09bee6,0x3f80bf7e,0xbcc93dfb,0x3f39bf4a,0x3f31bf1d,0x3f803f80,0x3f803f80,0x3f803f80,0x3f803f80,
0x0,0x0,0x0,0x0,0x3f803f80,0x3f803f80,0x3f803f80,0x3f803f80,0x0,0x0,0x0,0x0,
0x3f803f80,0x3f803f80,0x3f803f80,0x3f803f80,0x0,0x0,0x0,0x0,0x3f803f80,0x3f803f80,0x3f803f80,0x3f803f80,
0x0,0x0,0x0,0x0,0x3e480000,0x3f0e3ec4,0x3f553f35,0x3f7b3f6d,0x3f7b3f80,0x3f553f6d,0x3f0e3f35,0x3e483ec4,
0x3f7b3f80,0x3f553f6d,0x3f0e3f35,0x3e483ec4,0xbe480000,0xbf0ebec4,0xbf55bf35,0xbf7bbf6d,0xbe480000,0xbf0ebec4,0xbf55bf35,0xbf7bbf6d,
0xbf7bbf80,0xbf55bf6d,0xbf0ebf35,0xbe48bec4,0xbf7bbf80,0xbf55bf6d,0xbf0ebf35,0xbe48bec4,0x3e480000,0x3f0e3ec4,0x3f553f35,0x3f7b3f6d,
0xbf6dbf80,0xbec4bf35,0x3ec40000,0x3f6d3f35,0xbec40000,0xbf6dbf35,0xbf6dbf80,0xbec4bf35,0x3f6d3f80,0x3ec43f35,0xbec40000,0xbf6dbf35,
0x3ec40000,0x3f6d3f35,0x3f6d3f80,0x3ec43f35,0xbf6dbf80,0xbec4bf35,0x3ec40000,0x3f6d3f35,0xbec40000,0xbf6dbf35,0xbf6dbf80,0xbec4bf35,
0x3f6d3f80,0x3ec43f35,0xbec40000,0xbf6dbf35,0x3ec40000,0x3f6d3f35,0x3f6d3f80,0x3ec43f35,0xbf55bf80,0x3e48bec4,0x3f7b3f35,0x3f0e3f6d,
0x3f0e0000,0x3f7b3f6d,0x3e483f35,0xbf55bec4,0x3f0e0000,0x3f7b3f6d,0x3e483f35,0xbf55bec4,0x3f553f80,0xbe483ec4,0xbf7bbf35,0xbf0ebf6d,
0x3f553f80,0xbe483ec4,0xbf7bbf35,0xbf0ebf6d,0xbf0e0000,0xbf7bbf6d,0xbe48bf35,0x3f553ec4,0xbf0e0000,0xbf7bbf6d,0xbe48bf35,0x3f553ec4,
0xbf55bf80,0x3e48bec4,0x3f7b3f35,0x3f0e3f6d,0x3f353f80,0xbf350000,0xbf35bf80,0x3f350000,0x3f350000,0x3f353f80,0xbf350000,0xbf35bf80,
0x3f353f80,0xbf350000,0xbf35bf80,0x3f350000,0x3f350000,0x3f353f80,0xbf350000,0xbf35bf80,0x3f353f80,0xbf350000,0xbf35bf80,0x3f350000,
0x3f350000,0x3f353f80,0xbf350000,0xbf35bf80,0x3f353f80,0xbf350000,0xbf35bf80,0x3f350000,0x3f350000,0x3f353f80,0xbf350000,0xbf35bf80,
0xbf550000,0xbe48bf6d,0x3f7b3f35,0xbf0e3ec4,0xbf0ebf80,0x3f7b3ec4,0xbe483f35,0xbf55bf6d,0xbf0ebf80,0x3f7b3ec4,0xbe483f35,0xbf55bf6d,
0x3f550000,0x3e483f6d,0xbf7bbf35,0x3f0ebec4,0x3f550000,0x3e483f6d,0xbf7bbf35,0x3f0ebec4,0x3f0e3f80,0xbf7bbec4,0x3e48bf35,0x3f553f6d,
0x3f0e3f80,0xbf7bbec4,0x3e48bf35,0x3f553f6d,0xbf550000,0xbe48bf6d,0x3f7b3f35,0xbf0e3ec4,0xbec4bf80,0x3f6d3f35,0xbf6d0000,0x3ec4bf35,
0xbf6d0000,0x3ec4bf35,0x3ec43f80,0xbf6dbf35,0x3ec43f80,0xbf6dbf35,0x3f6d0000,0xbec43f35,0x3f6d0000,0xbec43f35,0xbec4bf80,0x3f6d3f35,
0xbec4bf80,0x3f6d3f35,0xbf6d0000,0x3ec4bf35,0xbf6d0000,0x3ec4bf35,0x3ec43f80,0xbf6dbf35,0x3ec43f80,0xbf6dbf35,0x3f6d0000,0xbec43f35,
0x3f6d0000,0xbec43f35,0xbec4bf80,0x3f6d3f35,0x3e483f80,0xbf0ebf6d,0x3f553f35,0xbf7bbec4,0xbf7b0000,0x3f55bec4,0xbf0e3f35,0x3e48bf6d,
0xbf7b0000,0x3f55bec4,0xbf0e3f35,0x3e48bf6d,0xbe48bf80,0x3f0e3f6d,0xbf55bf35,0x3f7b3ec4,0xbe48bf80,0x3f0e3f6d,0xbf55bf35,0x3f7b3ec4,
0x3f7b0000,0xbf553ec4,0x3f0ebf35,0xbe483f6d,0x3f7b0000,0xbf553ec4,0x3f0ebf35,0xbe483f6d,0x3e483f80,0xbf0ebf6d,0x3f553f35,0xbf7bbec4,
0x80008000,0x80008000,0x80008000,0x80008000,0x3f803f80,0x3f803f80,0x3f803f80,0x3f803f80,0x80008000,0x80008000,0x80008000,0x80008000,
0x3f803f80,0x3f803f80,0x3f803f80,0x3f803f80,0x80008000,0x80008000,0x80008000,0x80008000,0x3f803f80,0x3f803f80,0x3f803f80,0x3f803f80,
0x80008000,0x80008000,0x80008000,0x80008000,0x3f803f80,0x3f803f80,0x3f803f80,0x3f803f80,0x3f7b3f80,0x3f553f6d,0x3f0e3f35,0x3e483ec4,
0xbe488000,0xbf0ebec4,0xbf55bf35,0xbf7bbf6d,0xbe480000,0xbf0ebec4,0xbf55bf35,0xbf7bbf6d,0xbf7bbf80,0xbf55bf6d,0xbf0ebf35,0xbe48bec4,
0xbf7bbf80,0xbf55bf6d,0xbf0ebf35,0xbe48bec4,0x3e488000,0x3f0e3ec4,0x3f553f35,0x3f7b3f6d,0x3e480000,0x3f0e3ec4,0x3f553f35,0x3f7b3f6d,
0x3f7b3f80,0x3f553f6d,0x3f0e3f35,0x3e483ec4,0x3ec48000,0x3f6d3f35,0x3f6d3f80,0x3ec43f35,0xbf6dbf80,0xbec4bf35,0x3ec40000,0x3f6d3f35,
0xbec48000,0xbf6dbf35,0xbf6dbf80,0xbec4bf35,0x3f6d3f80,0x3ec43f35,0xbec40000,0xbf6dbf35,0x3ec48000,0x3f6d3f35,0x3f6d3f80,0x3ec43f35,
0xbf6dbf80,0xbec4bf35,0x3ec40000,0x3f6d3f35,0xbec48000,0xbf6dbf35,0xbf6dbf80,0xbec4bf35,0x3f6d3f80,0x3ec43f35,0xbec40000,0xbf6dbf35,
0x3f0e0000,0x3f7b3f6d,0x3e483f35,0xbf55bec4,0x3f553f80,0xbe483ec4,0xbf7bbf35,0xbf0ebf6d,0x3f553f80,0xbe483ec4,0xbf7bbf35,0xbf0ebf6d,
0xbf0e8000,0xbf7bbf6d,0xbe48bf35,0x3f553ec4,0xbf0e0000,0xbf7bbf6d,0xbe48bf35,0x3f553ec4,0xbf55bf80,0x3e48bec4,0x3f7b3f35,0x3f0e3f6d,
0xbf55bf80,0x3e48bec4,0x3f7b3f35,0x3f0e3f6d,0x3f0e8000,0x3f7b3f6d,0x3e483f35,0xbf55bec4,0xbf358000,0xbf35bf80,0x3f358000,0x3f353f80,
0x3f353f80,0xbf350000,0xbf35bf80,0x3f350000,0xbf358000,0xbf35bf80,0x3f358000,0x3f353f80,0x3f353f80,0xbf350000,0xbf35bf80,0x3f350000,
0xbf358000,0xbf35bf80,0x3f358000,0x3f353f80,0x3f353f80,0xbf350000,0xbf35bf80,0x3f350000,0xbf358000,0xbf35bf80,0x3f358000,0x3f353f80,
0x3f353f80,0xbf350000,0xbf35bf80,0x3f350000,0xbf0ebf80,0x3f7b3ec4,0xbe483f35,0xbf55bf6d,0x3f558000,0x3e483f6d,0xbf7bbf35,0x3f0ebec4,
0x3f550000,0x3e483f6d,0xbf7bbf35,0x3f0ebec4,0x3f0e3f80,0xbf7bbec4,0x3e48bf35,0x3f553f6d,0x3f0e3f80,0xbf7bbec4,0x3e48bf35,0x3f553f6d,
0xbf558000,0xbe48bf6d,0x3f7b3f35,0xbf0e3ec4,0xbf550000,0xbe48bf6d,0x3f7b3f35,0xbf0e3ec4,0xbf0ebf80,0x3f7b3ec4,0xbe483f35,0xbf55bf6d,
0x3f6d8000,0xbec43f35,0xbec4bf80,0x3f6d3f35,0xbec4bf80,0x3f6d3f35,0xbf6d0000,0x3ec4bf35,0xbf6d8000,0x3ec4bf35,0x3ec43f80,0xbf6dbf35,
0x3ec43f80,0xbf6dbf35,0x3f6d0000,0xbec43f35,0x3f6d8000,0xbec43f35,0xbec4bf80,0x3f6d3f35,0xbec4bf80,0x3f6d3f35,0xbf6d0000,0x3ec4bf35,
0xbf6d8000,0x3ec4bf35,0x3ec43f80,0xbf6dbf35,0x3ec43f80,0xbf6dbf35,0x3f6d0000,0xbec43f35,0xbf7b0000,0x3f55bec4,0xbf0e3f35,0x3e48bf6d,
0xbe48bf80,0x3f0e3f6d,0xbf55bf35,0x3f7b3ec4,0xbe48bf80,0x3f0e3f6d,0xbf55bf35,0x3f7b3ec4,0x3f7b8000,0xbf553ec4,0x3f0ebf35,0xbe483f6d,
0x3f7b0000,0xbf553ec4,0x3f0ebf35,0xbe483f6d,0x3e483f80,0xbf0ebf6d,0x3f553f35,0xbf7bbec4,0x3e483f80,0xbf0ebf6d,0x3f553f35,0xbf7bbec4,
0xbf7b8000,0x3f55bec4,0xbf0e3f35,0x3e48bf6d,0x3f80,0xbf80,0x3f80,0xbf80,0x3f800000,0xbf800000,0x3f800000,0xbf800000,
0x3f80,0xbf80,0x3f80,0xbf80,0x3f800000,0xbf800000,0x3f800000,0xbf800000,0x3f80,0xbf80,0x3f80,0xbf80,
0x3f800000,0xbf800000,0x3f800000,0xbf800000,0x3f80,0xbf80,0x3f80,0xbf80,0x3f800000,0xbf800000,0x3f800000,0xbf800000,
0x3f7b0000,0xbf55bec4,0x3f0e3f35,0xbe48bf6d,0xbe483f80,0x3f0ebf6d,0xbf553f35,0x3f7bbec4,0xbe483f80,0x3f0ebf6d,0xbf553f35,0x3f7bbec4,
0xbf7b0000,0x3f553ec4,0xbf0ebf35,0x3e483f6d,0xbf7b0000,0x3f553ec4,0xbf0ebf35,0x3e483f6d,0x3e48bf80,0xbf0e3f6d,0x3f55bf35,0xbf7b3ec4,
0x3e48bf80,0xbf0e3f6d,0x3f55bf35,0xbf7b3ec4,0x3f7b0000,0xbf55bec4,0x3f0e3f35,0xbe48bf6d,0x3ec4bf80,0xbf6d3f35,0x3f6d0000,0xbec4bf35,
0xbf6d0000,0x3ec43f35,0x3ec4bf80,0xbf6d3f35,0xbec43f80,0x3f6dbf35,0xbf6d0000,0x3ec43f35,0x3f6d0000,0xbec4bf35,0xbec43f80,0x3f6dbf35,
0x3ec4bf80,0xbf6d3f35,0x3f6d0000,0xbec4bf35,0xbf6d0000,0x3ec43f35,0x3ec4bf80,0xbf6d3f35,0xbec43f80,0x3f6dbf35,0xbf6d0000,0x3ec43f35,
0x3f6d0000,0xbec4bf35,0xbec43f80,0x3f6dbf35,0x3f0ebf80,0xbf7b3ec4,0x3e483f35,0x3f55bf6d,0x3f550000,0x3e48bf6d,0xbf7b3f35,0x3f0e3ec4,
0x3f550000,0x3e48bf6d,0xbf7b3f35,0x3f0e3ec4,0xbf0e3f80,0x3f7bbec4,0xbe48bf35,0xbf553f6d,0xbf0e3f80,0x3f7bbec4,0xbe48bf35,0xbf553f6d,
0xbf550000,0xbe483f6d,0x3f7bbf35,0xbf0ebec4,0xbf550000,0xbe483f6d,0x3f7bbf35,0xbf0ebec4,0x3f0ebf80,0xbf7b3ec4,0x3e483f35,0x3f55bf6d,
0xbf353f80,0x3f350000,0x3f35bf80,0xbf350000,0x3f350000,0x3f35bf80,0xbf350000,0xbf353f80,0xbf353f80,0x3f350000,0x3f35bf80,0xbf350000,
0x3f350000,0x3f35bf80,0xbf350000,0xbf353f80,0xbf353f80,0x3f350000,0x3f35bf80,0xbf350000,0x3f350000,0x3f35bf80,0xbf350000,0xbf353f80,
0xbf353f80,0x3f350000,0x3f35bf80,0xbf350000,0x3f350000,0x3f35bf80,0xbf350000,0xbf353f80,0xbf0e0000,0xbf7b3f6d,0xbe483f35,0x3f55bec4,
0x3f55bf80,0xbe48bec4,0xbf7b3f35,0xbf0e3f6d,0x3f55bf80,0xbe48bec4,0xbf7b3f35,0xbf0e3f6d,0x3f0e0000,0x3f7bbf6d,0x3e48bf35,0xbf553ec4,
0x3f0e0000,0x3f7bbf6d,0x3e48bf35,0xbf553ec4,0xbf553f80,0x3e483ec4,0x3f7bbf35,0x3f0ebf6d,0xbf553f80,0x3e483ec4,0x3f7bbf35,0x3f0ebf6d,
0xbf0e0000,0xbf7b3f6d,0xbe483f35,0x3f55bec4,0x3f6dbf80,0x3ec4bf35,0xbec40000,0xbf6d3f35,0xbec40000,0xbf6d3f35,0xbf6d3f80,0xbec43f35,
0xbf6d3f80,0xbec43f35,0x3ec40000,0x3f6dbf35,0x3ec40000,0x3f6dbf35,0x3f6dbf80,0x3ec4bf35,0x3f6dbf80,0x3ec4bf35,0xbec40000,0xbf6d3f35,
0xbec40000,0xbf6d3f35,0xbf6d3f80,0xbec43f35,0xbf6d3f80,0xbec43f35,0x3ec40000,0x3f6dbf35,0x3ec40000,0x3f6dbf35,0x3f6dbf80,0x3ec4bf35,
0xbf7b3f80,0xbf553f6d,0xbf0e3f35,0xbe483ec4,0xbe480000,0xbf0e3ec4,0xbf553f35,0xbf7b3f6d,0xbe480000,0xbf0e3ec4,0xbf553f35,0xbf7b3f6d,
0x3f7bbf80,0x3f55bf6d,0x3f0ebf35,0x3e48bec4,0x3f7bbf80,0x3f55bf6d,0x3f0ebf35,0x3e48bec4,0x3e480000,0x3f0ebec4,0x3f55bf35,0x3f7bbf6d,
0x3e480000,0x3f0ebec4,0x3f55bf35,0x3f7bbf6d,0xbf7b3f80,0xbf553f6d,0xbf0e3f35,0xbe483ec4,0xbf808000,0x3f808000,0xbf808000,0x3f808000,
0x3f80,0xbf80,0x3f80,0xbf80,0xbf808000,0x3f808000,0xbf808000,0x3f808000,0x3f80,0xbf80,0x3f80,0xbf80,
0xbf808000,0x3f808000,0xbf808000,0x3f808000,0x3f80,0xbf80,0x3f80,0xbf80,0xbf808000,0x3f808000,0xbf808000,0x3f808000,
0x3f80,0xbf80,0x3f80,0xbf80,0xbe483f80,0x3f0ebf6d,0xbf553f35,0x3f7bbec4,0xbf7b8000,0x3f553ec4,0xbf0ebf35,0x3e483f6d,
0xbf7b0000,0x3f553ec4,0xbf0ebf35,0x3e483f6d,0x3e48bf80,0xbf0e3f6d,0x3f55bf35,0xbf7b3ec4,0x3e48bf80,0xbf0e3f6d,0x3f55bf35,0xbf7b3ec4,
0x3f7b8000,0xbf55bec4,0x3f0e3f35,0xbe48bf6d,0x3f7b0000,0xbf55bec4,0x3f0e3f35,0xbe48bf6d,0xbe483f80,0x3f0ebf6d,0xbf553f35,0x3f7bbec4,
0x3f6d8000,0xbec4bf35,0xbec43f80,0x3f6dbf35,0x3ec4bf80,0xbf6d3f35,0x3f6d0000,0xbec4bf35,0xbf6d8000,0x3ec43f35,0x3ec4bf80,0xbf6d3f35,
0xbec43f80,0x3f6dbf35,0xbf6d0000,0x3ec43f35,0x3f6d8000,0xbec4bf35,0xbec43f80,0x3f6dbf35,0x3ec4bf80,0xbf6d3f35,0x3f6d0000,0xbec4bf35,
0xbf6d8000,0x3ec43f35,0x3ec4bf80,0xbf6d3f35,0xbec43f80,0x3f6dbf35,0xbf6d0000,0x3ec43f35,0x3f550000,0x3e48bf6d,0xbf7b3f35,0x3f0e3ec4,
0xbf0e3f80,0x3f7bbec4,0xbe48bf35,0xbf553f6d,0xbf0e3f80,0x3f7bbec4,0xbe48bf35,0xbf553f6d,0xbf558000,0xbe483f6d,0x3f7bbf35,0xbf0ebec4,
0xbf550000,0xbe483f6d,0x3f7bbf35,0xbf0ebec4,0x3f0ebf80,0xbf7b3ec4,0x3e483f35,0x3f55bf6d,0x3f0ebf80,0xbf7b3ec4,0x3e483f35,0x3f55bf6d,
0x3f558000,0x3e48bf6d,0xbf7b3f35,0x3f0e3ec4,0xbf358000,0xbf353f80,0x3f358000,0x3f35bf80,0xbf353f80,0x3f350000,0x3f35bf80,0xbf350000,
0xbf358000,0xbf353f80,0x3f358000,0x3f35bf80,0xbf353f80,0x3f350000,0x3f35bf80,0xbf350000,0xbf358000,0xbf353f80,0x3f358000,0x3f35bf80,
0xbf353f80,0x3f350000,0x3f35bf80,0xbf350000,0xbf358000,0xbf353f80,0x3f358000,0x3f35bf80,0xbf353f80,0x3f350000,0x3f35bf80,0xbf350000,
0x3f55bf80,0xbe48bec4,0xbf7b3f35,0xbf0e3f6d,0x3f0e8000,0x3f7bbf6d,0x3e48bf35,0xbf553ec4,0x3f0e0000,0x3f7bbf6d,0x3e48bf35,0xbf553ec4,
0xbf553f80,0x3e483ec4,0x3f7bbf35,0x3f0ebf6d,0xbf553f80,0x3e483ec4,0x3f7bbf35,0x3f0ebf6d,0xbf0e8000,0xbf7b3f6d,0xbe483f35,0x3f55bec4,
0xbf0e0000,0xbf7b3f6d,0xbe483f35,0x3f55bec4,0x3f55bf80,0xbe48bec4,0xbf7b3f35,0xbf0e3f6d,0x3ec48000,0x3f6dbf35,0x3f6dbf80,0x3ec4bf35,
0x3f6dbf80,0x3ec4bf35,0xbec40000,0xbf6d3f35,0xbec48000,0xbf6d3f35,0xbf6d3f80,0xbec43f35,0xbf6d3f80,0xbec43f35,0x3ec40000,0x3f6dbf35,
0x3ec48000,0x3f6dbf35,0x3f6dbf80,0x3ec4bf35,0x3f6dbf80,0x3ec4bf35,0xbec40000,0xbf6d3f35,0xbec48000,0xbf6d3f35,0xbf6d3f80,0xbec43f35,
0xbf6d3f80,0xbec43f35,0x3ec40000,0x3f6dbf35,0xbe480000,0xbf0e3ec4,0xbf553f35,0xbf7b3f6d,0x3f7bbf80,0x3f55bf6d,0x3f0ebf35,0x3e48bec4,
0x3f7bbf80,0x3f55bf6d,0x3f0ebf35,0x3e48bec4,0x3e488000,0x3f0ebec4,0x3f55bf35,0x3f7bbf6d,0x3e480000,0x3f0ebec4,0x3f55bf35,0x3f7bbf6d,
0xbf7b3f80,0xbf553f6d,0xbf0e3f35,0xbe483ec4,0xbf7b3f80,0xbf553f6d,0xbf0e3f35,0xbe483ec4,0xbe488000,0xbf0e3ec4,0xbf553f35,0xbf7b3f6d,
0xbf803f80,0xbf803f80,0xbf803f80,0xbf803f80,0x0,0x0,0x0,0x0,0xbf803f80,0xbf803f80,0xbf803f80,0xbf803f80,
0x0,0x0,0x0,0x0,0xbf803f80,0xbf803f80,0xbf803f80,0xbf803f80,0x0,0x0,0x0,0x0,
0xbf803f80,0xbf803f80,0xbf803f80,0xbf803f80,0x0,0x0,0x0,0x0,0xbe480000,0xbf0e3ec4,0xbf553f35,0xbf7b3f6d,
0xbf7b3f80,0xbf553f6d,0xbf0e3f35,0xbe483ec4,0xbf7b3f80,0xbf553f6d,0xbf0e3f35,0xbe483ec4,0x3e480000,0x3f0ebec4,0x3f55bf35,0x3f7bbf6d,
0x3e480000,0x3f0ebec4,0x3f55bf35,0x3f7bbf6d,0x3f7bbf80,0x3f55bf6d,0x3f0ebf35,0x3e48bec4,0x3f7bbf80,0x3f55bf6d,0x3f0ebf35,0x3e48bec4,
0xbe480000,0xbf0e3ec4,0xbf553f35,0xbf7b3f6d,0x3f6dbf80,0x3ec4bf35,0xbec40000,0xbf6d3f35,0x3ec40000,0x3f6dbf35,0x3f6dbf80,0x3ec4bf35,
0xbf6d3f80,0xbec43f35,0x3ec40000,0x3f6dbf35,0xbec40000,0xbf6d3f35,0xbf6d3f80,0xbec43f35,0x3f6dbf80,0x3ec4bf35,0xbec40000,0xbf6d3f35,
0x3ec40000,0x3f6dbf35,0x3f6dbf80,0x3ec4bf35,0xbf6d3f80,0xbec43f35,0x3ec40000,0x3f6dbf35,0xbec40000,0xbf6d3f35,0xbf6d3f80,0xbec43f35,
0x3f55bf80,0xbe48bec4,0xbf7b3f35,0xbf0e3f6d,0xbf0e0000,0xbf7b3f6d,0xbe483f35,0x3f55bec4,0xbf0e0000,0xbf7b3f6d,0xbe483f35,0x3f55bec4,
0xbf553f80,0x3e483ec4,0x3f7bbf35,0x3f0ebf6d,0xbf553f80,0x3e483ec4,0x3f7bbf35,0x3f0ebf6d,0x3f0e0000,0x3f7bbf6d,0x3e48bf35,0xbf553ec4,
0x3f0e0000,0x3f7bbf6d,0x3e48bf35,0xbf553ec4,0x3f55bf80,0xbe48bec4,0xbf7b3f35,0xbf0e3f6d,0xbf353f80,0x3f350000,0x3f35bf80,0xbf350000,
0xbf350000,0xbf353f80,0x3f350000,0x3f35bf80,0xbf353f80,0x3f350000,0x3f35bf80,0xbf350000,0xbf350000,0xbf353f80,0x3f350000,0x3f35bf80,
0xbf353f80,0x3f350000,0x3f35bf80,0xbf350000,0xbf350000,0xbf353f80,0x3f350000,0x3f35bf80,0xbf353f80,0x3f350000,0x3f35bf80,0xbf350000,
0xbf350000,0xbf353f80,0x3f350000,0x3f35bf80,0x3f550000,0x3e48bf6d,0xbf7b3f35,0x3f0e3ec4,0x3f0ebf80,0xbf7b3ec4,0x3e483f35,0x3f55bf6d,
0x3f0ebf80,0xbf7b3ec4,0x3e483f35,0x3f55bf6d,0xbf550000,0xbe483f6d,0x3f7bbf35,0xbf0ebec4,0xbf550000,0xbe483f6d,0x3f7bbf35,0xbf0ebec4,
0xbf0e3f80,0x3f7bbec4,0xbe48bf35,0xbf553f6d,0xbf0e3f80,0x3f7bbec4,0xbe48bf35,0xbf553f6d,0x3f550000,0x3e48bf6d,0xbf7b3f35,0x3f0e3ec4,
0x3ec4bf80,0xbf6d3f35,0x3f6d0000,0xbec4bf35,0x3f6d0000,0xbec4bf35,0xbec43f80,0x3f6dbf35,0xbec43f80,0x3f6dbf35,0xbf6d0000,0x3ec43f35,
0xbf6d0000,0x3ec43f35,0x3ec4bf80,0xbf6d3f35,0x3ec4bf80,0xbf6d3f35,0x3f6d0000,0xbec4bf35,0x3f6d0000,0xbec4bf35,0xbec43f80,0x3f6dbf35,
0xbec43f80,0x3f6dbf35,0xbf6d0000,0x3ec43f35,0xbf6d0000,0x3ec43f35,0x3ec4bf80,0xbf6d3f35,0xbe483f80,0x3f0ebf6d,0xbf553f35,0x3f7bbec4,
0x3f7b0000,0xbf55bec4,0x3f0e3f35,0xbe48bf6d,0x3f7b0000,0xbf55bec4,0x3f0e3f35,0xbe48bf6d,0x3e48bf80,0xbf0e3f6d,0x3f55bf35,0xbf7b3ec4,
0x3e48bf80,0xbf0e3f6d,0x3f55bf35,0xbf7b3ec4,0xbf7b0000,0x3f553ec4,0xbf0ebf35,0x3e483f6d,0xbf7b0000,0x3f553ec4,0xbf0ebf35,0x3e483f6d,
0xbe483f80,0x3f0ebf6d,0xbf553f35,0x3f7bbec4,0x80008000,0x80008000,0x80008000,0x80008000,0xbf803f80,0xbf803f80,0xbf803f80,0xbf803f80,
0x80008000,0x80008000,0x80008000,0x80008000,0xbf803f80,0xbf803f80,0xbf803f80,0xbf803f80,0x80008000,0x80008000,0x80008000,0x80008000,
0xbf803f80,0xbf803f80,0xbf803f80,0xbf803f80,0x80008000,0x80008000,0x80008000,0x80008000,0xbf803f80,0xbf803f80,0xbf803f80,0xbf803f80,
0xbf7b3f80,0xbf553f6d,0xbf0e3f35,0xbe483ec4,0x3e488000,0x3f0ebec4,0x3f55bf35,0x3f7bbf6d,0x3e480000,0x3f0ebec4,0x3f55bf35,0x3f7bbf6d,
0x3f7bbf80,0x3f55bf6d,0x3f0ebf35,0x3e48bec4,0x3f7bbf80,0x3f55bf6d,0x3f0ebf35,0x3e48bec4,0xbe488000,0xbf0e3ec4,0xbf553f35,0xbf7b3f6d,
0xbe480000,0xbf0e3ec4,0xbf553f35,0xbf7b3f6d,0xbf7b3f80,0xbf553f6d,0xbf0e3f35,0xbe483ec4,0xbec48000,0xbf6d3f35,0xbf6d3f80,0xbec43f35,
0x3f6dbf80,0x3ec4bf35,0xbec40000,0xbf6d3f35,0x3ec48000,0x3f6dbf35,0x3f6dbf80,0x3ec4bf35,0xbf6d3f80,0xbec43f35,0x3ec40000,0x3f6dbf35,
0xbec48000,0xbf6d3f35,0xbf6d3f80,0xbec43f35,0x3f6dbf80,0x3ec4bf35,0xbec40000,0xbf6d3f35,0x3ec48000,0x3f6dbf35,0x3f6dbf80,0x3ec4bf35,
0xbf6d3f80,0xbec43f35,0x3ec40000,0x3f6dbf35,0xbf0e0000,0xbf7b3f6d,0xbe483f35,0x3f55bec4,0xbf553f80,0x3e483ec4,0x3f7bbf35,0x3f0ebf6d,
0xbf553f80,0x3e483ec4,0x3f7bbf35,0x3f0ebf6d,0x3f0e8000,0x3f7bbf6d,0x3e48bf35,0xbf553ec4,0x3f0e0000,0x3f7bbf6d,0x3e48bf35,0xbf553ec4,
0x3f55bf80,0xbe48bec4,0xbf7b3f35,0xbf0e3f6d,0x3f55bf80,0xbe48bec4,0xbf7b3f35,0xbf0e3f6d,0xbf0e8000,0xbf7b3f6d,0xbe483f35,0x3f55bec4,
0x3f358000,0x3f35bf80,0xbf358000,0xbf353f80,0xbf353f80,0x3f350000,0x3f35bf80,0xbf350000,0x3f358000,0x3f35bf80,0xbf358000,0xbf353f80,
0xbf353f80,0x3f350000,0x3f35bf80,0xbf350000,0x3f358000,0x3f35bf80,0xbf358000,0xbf353f80,0xbf353f80,0x3f350000,0x3f35bf80,0xbf350000,
0x3f358000,0x3f35bf80,0xbf358000,0xbf353f80,0xbf353f80,0x3f350000,0x3f35bf80,0xbf350000,0x3f0ebf80,0xbf7b3ec4,0x3e483f35,0x3f55bf6d,
0xbf558000,0xbe483f6d,0x3f7bbf35,0xbf0ebec4,0xbf550000,0xbe483f6d,0x3f7bbf35,0xbf0ebec4,0xbf0e3f80,0x3f7bbec4,0xbe48bf35,0xbf553f6d,
0xbf0e3f80,0x3f7bbec4,0xbe48bf35,0xbf553f6d,0x3f558000,0x3e48bf6d,0xbf7b3f35,0x3f0e3ec4,0x3f550000,0x3e48bf6d,0xbf7b3f35,0x3f0e3ec4,
0x3f0ebf80,0xbf7b3ec4,0x3e483f35,0x3f55bf6d,0xbf6d8000,0x3ec43f35,0x3ec4bf80,0xbf6d3f35,0x3ec4bf80,0xbf6d3f35,0x3f6d0000,0xbec4bf35,
0x3f6d8000,0xbec4bf35,0xbec43f80,0x3f6dbf35,0xbec43f80,0x3f6dbf35,0xbf6d0000,0x3ec43f35,0xbf6d8000,0x3ec43f35,0x3ec4bf80,0xbf6d3f35,
0x3ec4bf80,0xbf6d3f35,0x3f6d0000,0xbec4bf35,0x3f6d8000,0xbec4bf35,0xbec43f80,0x3f6dbf35,0xbec43f80,0x3f6dbf35,0xbf6d0000,0x3ec43f35,
0x3f7b0000,0xbf55bec4,0x3f0e3f35,0xbe48bf6d,0x3e48bf80,0xbf0e3f6d,0x3f55bf35,0xbf7b3ec4,0x3e48bf80,0xbf0e3f6d,0x3f55bf35,0xbf7b3ec4,
0xbf7b8000,0x3f553ec4,0xbf0ebf35,0x3e483f6d,0xbf7b0000,0x3f553ec4,0xbf0ebf35,0x3e483f6d,0xbe483f80,0x3f0ebf6d,0xbf553f35,0x3f7bbec4,
0xbe483f80,0x3f0ebf6d,0xbf553f35,0x3f7bbec4,0x3f7b8000,0xbf55bec4,0x3f0e3f35,0xbe48bf6d,0x3f80,0xbf80,0x3f80,0xbf80,
0xbf800000,0x3f800000,0xbf800000,0x3f800000,0x3f80,0xbf80,0x3f80,0xbf80,0xbf800000,0x3f800000,0xbf800000,0x3f800000,
0x3f80,0xbf80,0x3f80,0xbf80,0xbf800000,0x3f800000,0xbf800000,0x3f800000,0x3f80,0xbf80,0x3f80,0xbf80,
0xbf800000,0x3f800000,0xbf800000,0x3f800000,0xbf7b0000,0x3f55bec4,0xbf0e3f35,0x3e48bf6d,0x3e483f80,0xbf0ebf6d,0x3f553f35,0xbf7bbec4,
0x3e483f80,0xbf0ebf6d,0x3f553f35,0xbf7bbec4,0x3f7b0000,0xbf553ec4,0x3f0ebf35,0xbe483f6d,0x3f7b0000,0xbf553ec4,0x3f0ebf35,0xbe483f6d,
0xbe48bf80,0x3f0e3f6d,0xbf55bf35,0x3f7b3ec4,0xbe48bf80,0x3f0e3f6d,0xbf55bf35,0x3f7b3ec4,0xbf7b0000,0x3f55bec4,0xbf0e3f35,0x3e48bf6d,
0xbec4bf80,0x3f6d3f35,0xbf6d0000,0x3ec4bf35,0x3f6d0000,0xbec43f35,0xbec4bf80,0x3f6d3f35,0x3ec43f80,0xbf6dbf35,0x3f6d0000,0xbec43f35,
0xbf6d0000,0x3ec4bf35,0x3ec43f80,0xbf6dbf35,0xbec4bf80,0x3f6d3f35,0xbf6d0000,0x3ec4bf35,0x3f6d0000,0xbec43f35,0xbec4bf80,0x3f6d3f35,
0x3ec43f80,0xbf6dbf35,0x3f6d0000,0xbec43f35,0xbf6d0000,0x3ec4bf35,0x3ec43f80,0xbf6dbf35,0xbf0ebf80,0x3f7b3ec4,0xbe483f35,0xbf55bf6d,
0xbf550000,0xbe48bf6d,0x3f7b3f35,0xbf0e3ec4,0xbf550000,0xbe48bf6d,0x3f7b3f35,0xbf0e3ec4,0x3f0e3f80,0xbf7bbec4,0x3e48bf35,0x3f553f6d,
0x3f0e3f80,0xbf7bbec4,0x3e48bf35,0x3f553f6d,0x3f550000,0x3e483f6d,0xbf7bbf35,0x3f0ebec4,0x3f550000,0x3e483f6d,0xbf7bbf35,0x3f0ebec4,
0xbf0ebf80,0x3f7b3ec4,0xbe483f35,0xbf55bf6d,0x3f353f80,0xbf350000,0xbf35bf80,0x3f350000,0xbf350000,0xbf35bf80,0x3f350000,0x3f353f80,
0x3f353f80,0xbf350000,0xbf35bf80,0x3f350000,0xbf350000,0xbf35bf80,0x3f350000,0x3f353f80,0x3f353f80,0xbf350000,0xbf35bf80,0x3f350000,
0xbf350000,0xbf35bf80,0x3f350000,0x3f353f80,0x3f353f80,0xbf350000,0xbf35bf80,0x3f350000,0xbf350000,0xbf35bf80,0x3f350000,0x3f353f80,
0x3f0e0000,0x3f7b3f6d,0x3e483f35,0xbf55bec4,0xbf55bf80,0x3e48bec4,0x3f7b3f35,0x3f0e3f6d,0xbf55bf80,0x3e48bec4,0x3f7b3f35,0x3f0e3f6d,
0xbf0e0000,0xbf7bbf6d,0xbe48bf35,0x3f553ec4,0xbf0e0000,0xbf7bbf6d,0xbe48bf35,0x3f553ec4,0x3f553f80,0xbe483ec4,0xbf7bbf35,0xbf0ebf6d,
0x3f553f80,0xbe483ec4,0xbf7bbf35,0xbf0ebf6d,0x3f0e0000,0x3f7b3f6d,0x3e483f35,0xbf55bec4,0xbf6dbf80,0xbec4bf35,0x3ec40000,0x3f6d3f35,
0x3ec40000,0x3f6d3f35,0x3f6d3f80,0x3ec43f35,0x3f6d3f80,0x3ec43f35,0xbec40000,0xbf6dbf35,0xbec40000,0xbf6dbf35,0xbf6dbf80,0xbec4bf35,
0xbf6dbf80,0xbec4bf35,0x3ec40000,0x3f6d3f35,0x3ec40000,0x3f6d3f35,0x3f6d3f80,0x3ec43f35,0x3f6d3f80,0x3ec43f35,0xbec40000,0xbf6dbf35,
0xbec40000,0xbf6dbf35,0xbf6dbf80,0xbec4bf35,0x3f7b3f80,0x3f553f6d,0x3f0e3f35,0x3e483ec4,0x3e480000,0x3f0e3ec4,0x3f553f35,0x3f7b3f6d,
0x3e480000,0x3f0e3ec4,0x3f553f35,0x3f7b3f6d,0xbf7bbf80,0xbf55bf6d,0xbf0ebf35,0xbe48bec4,0xbf7bbf80,0xbf55bf6d,0xbf0ebf35,0xbe48bec4,
0xbe480000,0xbf0ebec4,0xbf55bf35,0xbf7bbf6d,0xbe480000,0xbf0ebec4,0xbf55bf35,0xbf7bbf6d,0x3f7b3f80,0x3f553f6d,0x3f0e3f35,0x3e483ec4,
0x3f808000,0xbf808000,0x3f808000,0xbf808000,0x3f80,0xbf80,0x3f80,0xbf80,0x3f808000,0xbf808000,0x3f808000,0xbf808000,
0x3f80,0xbf80,0x3f80,0xbf80,0x3f808000,0xbf808000,0x3f808000,0xbf808000,0x3f80,0xbf80,0x3f80,0xbf80,
0x3f808000,0xbf808000,0x3f808000,0xbf808000,0x3f80,0xbf80,0x3f80,0xbf80,0x3e483f80,0xbf0ebf6d,0x3f553f35,0xbf7bbec4,
0x3f7b8000,0xbf553ec4,0x3f0ebf35,0xbe483f6d,0x3f7b0000,0xbf553ec4,0x3f0ebf35,0xbe483f6d,0xbe48bf80,0x3f0e3f6d,0xbf55bf35,0x3f7b3ec4,
0xbe48bf80,0x3f0e3f6d,0xbf55bf35,0x3f7b3ec4,0xbf7b8000,0x3f55bec4,0xbf0e3f35,0x3e48bf6d,0xbf7b0000,0x3f55bec4,0xbf0e3f35,0x3e48bf6d,
0x3e483f80,0xbf0ebf6d,0x3f553f35,0xbf7bbec4,0xbf6d8000,0x3ec4bf35,0x3ec43f80,0xbf6dbf35,0xbec4bf80,0x3f6d3f35,0xbf6d0000,0x3ec4bf35,
0x3f6d8000,0xbec43f35,0xbec4bf80,0x3f6d3f35,0x3ec43f80,0xbf6dbf35,0x3f6d0000,0xbec43f35,0xbf6d8000,0x3ec4bf35,0x3ec43f80,0xbf6dbf35,
0xbec4bf80,0x3f6d3f35,0xbf6d0000,0x3ec4bf35,0x3f6d8000,0xbec43f35,0xbec4bf80,0x3f6d3f35,0x3ec43f80,0xbf6dbf35,0x3f6d0000,0xbec43f35,
0xbf550000,0xbe48bf6d,0x3f7b3f35,0xbf0e3ec4,0x3f0e3f80,0xbf7bbec4,0x3e48bf35,0x3f553f6d,0x3f0e3f80,0xbf7bbec4,0x3e48bf35,0x3f553f6d,
0x3f558000,0x3e483f6d,0xbf7bbf35,0x3f0ebec4,0x3f550000,0x3e483f6d,0xbf7bbf35,0x3f0ebec4,0xbf0ebf80,0x3f7b3ec4,0xbe483f35,0xbf55bf6d,
0xbf0ebf80,0x3f7b3ec4,0xbe483f35,0xbf55bf6d,0xbf558000,0xbe48bf6d,0x3f7b3f35,0xbf0e3ec4,0x3f358000,0x3f353f80,0xbf358000,0xbf35bf80,
0x3f353f80,0xbf350000,0xbf35bf80,0x3f350000,0x3f358000,0x3f353f80,0xbf358000,0xbf35bf80,0x3f353f80,0xbf350000,0xbf35bf80,0x3f350000,
0x3f358000,0x3f353f80,0xbf358000,0xbf35bf80,0x3f353f80,0xbf350000,0xbf35bf80,0x3f350000,0x3f358000,0x3f353f80,0xbf358000,0xbf35bf80,
0x3f353f80,0xbf350000,0xbf35bf80,0x3f350000,0xbf55bf80,0x3e48bec4,0x3f7b3f35,0x3f0e3f6d,0xbf0e8000,0xbf7bbf6d,0xbe48bf35,0x3f553ec4,
0xbf0e0000,0xbf7bbf6d,0xbe48bf35,0x3f553ec4,0x3f553f80,0xbe483ec4,0xbf7bbf35,0xbf0ebf6d,0x3f553f80,0xbe483ec4,0xbf7bbf35,0xbf0ebf6d,
0x3f0e8000,0x3f7b3f6d,0x3e483f35,0xbf55bec4,0x3f0e0000,0x3f7b3f6d,0x3e483f35,0xbf55bec4,0xbf55bf80,0x3e48bec4,0x3f7b3f35,0x3f0e3f6d,
0xbec48000,0xbf6dbf35,0xbf6dbf80,0xbec4bf35,0xbf6dbf80,0xbec4bf35,0x3ec40000,0x3f6d3f35,0x3ec48000,0x3f6d3f35,0x3f6d3f80,0x3ec43f35,
0x3f6d3f80,0x3ec43f35,0xbec40000,0xbf6dbf35,0xbec48000,0xbf6dbf35,0xbf6dbf80,0xbec4bf35,0xbf6dbf80,0xbec4bf35,0x3ec40000,0x3f6d3f35,
0x3ec48000,0x3f6d3f35,0x3f6d3f80,0x3ec43f35,0x3f6d3f80,0x3ec43f35,0xbec40000,0xbf6dbf35,0x3e480000,0x3f0e3ec4,0x3f553f35,0x3f7b3f6d,
0xbf7bbf80,0xbf55bf6d,0xbf0ebf35,0xbe48bec4,0xbf7bbf80,0xbf55bf6d,0xbf0ebf35,0xbe48bec4,0xbe488000,0xbf0ebec4,0xbf55bf35,0xbf7bbf6d,
0xbe480000,0xbf0ebec4,0xbf55bf35,0xbf7bbf6d,0x3f7b3f80,0x3f553f6d,0x3f0e3f35,0x3e483ec4,0x3f7b3f80,0x3f553f6d,0x3f0e3f35,0x3e483ec4,
0x3e488000,0x3f0e3ec4,0x3f553f35,0x3f7b3f6d,0x3f803f80,0x80008000,0x3f803f80,0x80008000,0x3f803f80,0x80008000,0x3f803f80,0x80008000,
0x3f803f80,0x80008000,0x3f803f80,0x80008000,0x3f803f80,0x80008000,0x3f803f80,0x80008000,0x3f803f80,0xbbc98000,0x3f803f80,0xbd62bd49,
0x3f803f80,0xbc97bc49,0x3f7f3f80,0xbd8abd7b,0x3f803f80,0xbcfbbcc9,0x3f7f3f7f,0xbda3bd97,0x3f803f80,0xbd30bd17,0x3f7f3f7f,0xbdbcbdb0,
0x3f803f80,0xbc498000,0x3f7e3f7f,0xbde2bdc9,0x3f803f80,0xbd17bcc9,0x3f7e3f7e,0xbe0abdfb,0x3f803f80,0xbd7bbd49,0x3f7d3f7d,0xbe23be16,
0x3f7f3f7f,0xbdb0bd97,0x3f7c3f7c,0xbe3bbe2f,0x3f803f80,0xbc978000,0x3f7c3f7d,0xbe29be16,0x3f803f80,0xbd62bd17,0x3f7b3f7c,0xbe4ebe3b,
0x3f7f3f7f,0xbdbcbd97,0x3f793f7a,0xbe73be60,0x3f7e3f7e,0xbe04bde2,0x3f763f78,0xbe8cbe82,0x3f803f80,0xbcc98000,0x3f7a3f7b,0xbe60be48,
0x3f7f3f80,0xbd97bd49,0x3f773f78,0xbe89be79,0x3f7e3f7f,0xbdfbbdc9,0x3f733f75,0xbea1be95,0x3f7c3f7d,0xbe2fbe16,0x3f6f3f71,0xbeb8beac,
0x3f803f80,0xbcfb8000,0x3f763f78,0xbe8cbe79,0x3f7f3f80,0xbdbcbd7b,0x3f723f74,0xbeaabe9b,0x3f7d3f7e,0xbe1cbdfb,0x3f6c3f6f,0xbec7beb8,
0x3f7a3f7c,0xbe5abe3b,0x3f653f69,0xbee3bed5,0x3f803f80,0xbd178000,0x3f723f75,0xbea7be95,0x3f7e3f7f,0xbde2bd97,0x3f6b3f6f,0xbecabeb8,
0x3f7c3f7d,0xbe3bbe16,0x3f633f67,0xbeecbedb,0x3f783f7a,0xbe82be60,0x3f5a3f5f,0xbf06befc,0x3f803f80,0xbd308000,0x3f6d3f71,0xbec1beac,
0x3f7e3f7f,0xbe04bdb0,0x3f643f69,0xbee9bed5,0x3f7a3f7c,0xbe5abe2f,0x3f593f5f,0xbf08befc,0x3f753f78,0xbe98be82,0x3f4d3f53,0xbf1abf11,
0x3f803f80,0xbd498000,0x3f673f6d,0xbedbbec4,0x3f7d3f7f,0xbe16bdc9,0x3f5c3f62,0xbf04bef1,0x3f783f7b,0xbe79be48,0x3f4e3f55,0xbf18bf0e,
0x3f713f75,0xbeacbe95,0x3f3e3f46,0xbf2cbf22,0x3f803f80,0xbd628000,0x3f613f67,0xbef4bedb,0x3f7c3f7e,0xbe29bde2,0x3f523f5a,0xbf12bf06,
0x3f763f7a,0xbe8cbe60,0x3f413f4a,0xbf28bf1d,0x3f6d3f72,0xbec1bea7,0x3f2d3f37,0xbf3dbf33,0x3f803f80,0xbd7b8000,0x3f5a3f62,0xbf06bef1,
0x3f7c3f7e,0xbe3bbdfb,0x3f483f51,0xbf20bf13,0x3f743f78,0xbe9bbe79,0x3f333f3e,0xbf37bf2c,0x3f693f6f,0xbed5beb8,0x3f1b3f27,0xbf4cbf42,
0x3f7f3f80,0xbd8a8000,0x3f523f5c,0xbf12bf04,0x3f7b3f7e,0xbe4ebe0a,0x3f3d3f48,0xbf2dbf20,0x3f723f77,0xbeaabe89,0x3f243f31,0xbf45bf39,
0x3f643f6b,0xbee9beca,0x3f083f16,0xbf59bf4f,0x3f7f3f80,0xbd978000,0x3f4a3f55,0xbf1dbf0e,0x3f7a3f7d,0xbe60be16,0x3f313f3e,0xbf39bf2c,
0x3f6f3f75,0xbeb8be95,0x3f133f22,0xbf51bf46,0x3f5f3f67,0xbefcbedb,0x3ee63f04,0xbf65bf5c,0x3f7f3f80,0xbda38000,0x3f413f4e,0xbf28bf18,
0x3f793f7d,0xbe73be23,0x3f243f33,0xbf45bf37,0x3f6c3f73,0xbec7bea1,0x3f023f13,0xbf5cbf51,0x3f593f63,0xbf08beec,0x3ebb3ee1,0xbf6ebf66,
0x3f7f3f80,0xbdb08000,0x3f373f46,0xbf33bf22,0x3f783f7c,0xbe82be2f,0x3f163f27,0xbf4fbf42,0x3f693f71,0xbed5beac,0x3ee13f04,0xbf66bf5c,
0x3f533f5f,0xbf11befc,0x3e8f3eb8,0xbf76bf6f,0x3f7f3f80,0xbdbc8000,0x3f2d3f3e,0xbf3dbf2c,0x3f763f7c,0xbe8cbe3b,0x3f083f1b,0xbf59bf4c,
0x3f653f6f,0xbee3beb8,0x3ebb3ee6,0xbf6ebf65,0x3f4d3f5a,0xbf1abf06,0x3e423e8f,0xbf7bbf76,0x3f7f3f80,0xbdc98000,0x3f223f35,0xbf46bf35,
0x3f753f7b,0xbe95be48,0x3ef13f0e,0xbf62bf55,0x3f623f6d,0xbef1bec4,0x3e953ec4,0xbf75bf6d,0x3f463f55,0xbf22bf0e,0x3dc93e48,0xbf7fbf7b,
0x3f7f3f80,0xbdd58000,0x3f173f2c,0xbf4fbf3e,0x3f743f7a,0xbe9ebe54,0x3ed23f01,0xbf69bf5d,0x3f5e3f6a,0xbeffbecf,0x3e5a3ea1,0xbf7abf73,
0x3f3f3f4f,0xbf2bbf16,0x3bc93de2,0xbf80bf7e,0x3f7e3f80,0xbde28000,0x3f0c3f22,0xbf57bf46,0x3f723f7a,0xbea7be60,0x3eb23ee6,0xbf70bf65,
0x3f5a3f67,0xbf06bedb,0x3e0a3e79,0xbf7ebf78,0x3f373f4a,0xbf33bf1d,0xbdb03cc9,0xbf7fbf80,0x3f7e3f80,0xbdee8000,0x3eff3f18,0xbf5ebf4e,
0x3f713f79,0xbeafbe6d,0x3e923eca,0xbf75bf6b,0x3f563f65,0xbf0dbee6,0x3d623e2f,0xbf80bf7c,0x3f2f3f44,0xbf3abf25,0xbe35bd7b,0xbf7cbf80,
0x3f7e3f80,0xbdfb8000,0x3ee63f0e,0xbf65bf55,0x3f6f3f78,0xbeb8be79,0x3e603eac,0xbf7abf71,0x3f513f62,0xbf13bef1,0xbcc93dc9,0xbf80bf7f,
0x3f273f3e,0xbf42bf2c,0xbe89be16,0xbf77bf7d,0x3f7e3f80,0xbe048000,0x3ecd3f04,0xbf6bbf5c,0x3f6d3f78,0xbec1be82,0x3e1c3e8f,0xbf7dbf76,
0x3f4d3f5f,0xbf1abefc,0xbdd53cc9,0xbf7fbf80,0x3f1f3f37,0xbf49bf33,0xbeb5be6d,0xbf6fbf79,0x3f7e3f80,0xbe0a8000,0x3eb23ef1,0xbf70bf62,
0x3f6b3f77,0xbecabe89,0x3db03e60,0xbf7fbf7a,0x3f483f5c,0xbf20bf04,0xbe3bbd49,0xbf7cbf80,0x3f163f31,0xbf4fbf39,0xbee1bea1,0xbf66bf73,
0x3f7d3f80,0xbe108000,0x3e983edb,0xbf75bf67,0x3f693f76,0xbed2be8f,0x3c973e23,0xbf80bf7d,0x3f433f58,0xbf26bf09,0xbe86bdfb,0xbf77bf7e,
0x3f0d3f2a,0xbf56bf40,0xbf05beca,0xbf5bbf6b,0x3f7d3f80,0xbe168000,0x3e793ec4,0xbf78bf6d,0x3f673f75,0xbedbbe95,0xbd493dc9,0xbf80bf7f,
0x3f3e3f55,0xbf2cbf0e,0xbeacbe48,0xbf71bf7b,0x3f043f22,0xbf5cbf46,0xbf18bef1,0xbf4ebf62,0x3f7d3f80,0xbe1c8000,0x3e423eac,0xbf7bbf71,
0x3f653f74,0xbee3be9b,0xbdee3d17,0xbf7ebf80,0x3f383f51,0xbf32bf13,0xbed2be89,0xbf69bf77,0x3ef43f1b,0xbf61bf4c,0xbf2bbf0c,0xbf3fbf57,
0x3f7d3f80,0xbe238000,0x3e0a3e95,0xbf7ebf75,0x3f633f73,0xbeecbea1,0xbe3bbcc9,0xbf7cbf80,0x3f333f4e,0xbf37bf18,0xbef7beac,0xbf60bf71,
0x3ee13f13,0xbf66bf51,0xbf3cbf1d,0xbf2ebf4a,0x3f7c3f80,0xbe298000,0x3da33e79,0xbf7fbf78,0x3f613f72,0xbef4bea7,0xbe7fbdb0,0xbf78bf7f,
0x3f2d3f4a,0xbf3dbf1d,0xbf0dbecf,0xbf56bf6a,0x3ecd3f0c,0xbf6bbf57,0xbf4bbf2e,0xbf1cbf3c,0x3f7c3f80,0xbe2f8000,0x3cc93e48,0xbf80bf7b,
0x3f5f3f71,0xbefcbeac,0xbea1be16,0xbf73bf7d,0x3f273f46,0xbf42bf22,0xbf1dbef1,0xbf4abf62,0x3eb83f04,0xbf6fbf5c,0xbf58bf3e,0xbf09bf2c,
0x3f7c3f80,0xbe358000,0xbcfb3e16,0xbf80bf7d,0x3f5c3f70,0xbf02beb2,0xbec1be54,0xbf6dbf7a,0x3f213f42,0xbf47bf27,0xbf2dbf09,0xbf3dbf58,
0x3ea43ef7,0xbf73bf60,0xbf64bf4c,0xbee9bf1b,0x3f7c3f80,0xbe3b8000,0xbdb03dc9,0xbf7fbf7f,0x3f5a3f6f,0xbf06beb8,0xbee1be89,0xbf66bf77,
0x3f1b3f3e,0xbf4cbf2c,0xbf3cbf18,0xbf2ebf4e,0x3e8f3ee6,0xbf76bf65,0xbf6ebf58,0xbebebf09,0x3f7b3f80,0xbe428000,0xbe103d49,0xbf7dbf80,
0x3f573f6e,0xbf0abebe,0xbeffbea7,0xbf5ebf72,0x3f153f39,0xbf50bf31,0xbf49bf27,0xbf1fbf42,0x3e733ed5,0xbf79bf69,0xbf75bf63,0xbe92beec,
0x3f803f80,0x80008000,0x3f803f80,0x80008000,0x3f803f80,0x80008000,0x3f803f80,0x80008000,0x3f803f80,0x80008000,0x3f803f80,0x80008000,
0x3f803f80,0x80008000,0x3f803f80,0x80008000,0x3f7f3f7f,0xbdd5bdc9,0x3f7d3f7d,0xbe1cbe16,0x3f7e3f7e,0xbdeebde2,0x3f7c3f7d,0xbe29be23,
0x3f7e3f7e,0xbe04bdfb,0x3f7c3f7c,0xbe35be2f,0x3f7d3f7e,0xbe10be0a,0x3f7b3f7c,0xbe42be3b,0x3f7a3f7b,0xbe54be48,0x3f743f75,0xbe9bbe95,
0x3f793f7a,0xbe6dbe60,0x3f723f73,0xbea7bea1,0x3f783f78,0xbe82be79,0x3f703f71,0xbeb2beac,0x3f763f77,0xbe8fbe89,0x3f6e3f6f,0xbebebeb8,
0x3f743f75,0xbe9ebe95,0x3f653f67,0xbee3bedb,0x3f713f72,0xbeafbea7,0x3f613f63,0xbef4beec,0x3f6d3f6f,0xbec1beb8,0x3f5c3f5f,0xbf02befc,
0x3f693f6b,0xbed2beca,0x3f573f5a,0xbf0abf06,0x3f6a3f6d,0xbecfbec4,0x3f513f55,0xbf13bf0e,0x3f653f67,0xbee6bedb,0x3f4a3f4e,0xbf1dbf18,
0x3f5f3f62,0xbefcbef1,0x3f423f46,0xbf27bf22,0x3f583f5c,0xbf09bf04,0x3f393f3e,0xbf31bf2c,0x3f5e3f62,0xbeffbef1,0x3f383f3e,0xbf32bf2c,
0x3f563f5a,0xbf0dbf06,0x3f2d3f33,0xbf3dbf37,0x3f4d3f51,0xbf1abf13,0x3f213f27,0xbf47bf42,0x3f433f48,0xbf26bf20,0x3f153f1b,0xbf50bf4c,
0x3f4f3f55,0xbf16bf0e,0x3f1b3f22,0xbf4cbf46,0x3f443f4a,0xbf25bf1d,0x3f0c3f13,0xbf57bf51,0x3f373f3e,0xbf33bf2c,0x3ef73f04,0xbf60bf5c,
0x3f2a3f31,0xbf40bf39,0x3ed53ee6,0xbf69bf65,0x3f3f3f46,0xbf2bbf22,0x3ef43f04,0xbf61bf5c,0x3f2f3f37,0xbf3abf33,0x3ecd3ee1,0xbf6bbf66,
0x3f1f3f27,0xbf49bf42,0x3ea43eb8,0xbf73bf6f,0x3f0d3f16,0xbf56bf4f,0x3e733e8f,0xbf79bf76,0x3f2c3f35,0xbf3ebf35,0x3eac3ec4,0xbf71bf6d,
0x3f183f22,0xbf4ebf46,0x3e793e95,0xbf78bf75,0x3f043f0e,0xbf5cbf55,0x3e163e48,0xbf7dbf7b,0x3edb3ef1,0xbf67bf62,0x3d493dc9,0xbf80bf7f,
0x3f173f22,0xbf4fbf46,0x3e423e79,0xbf7bbf78,0x3eff3f0c,0xbf5ebf57,0x3da33e0a,0xbf7fbf7e,0x3ecd3ee6,0xbf6bbf65,0xbcfb3cc9,0xbf80bf80,
0x3e983eb2,0xbf75bf70,0xbe10bdb0,0xbf7dbf7f,0x3f013f0e,0xbf5dbf55,0x3d173dc9,0xbf80bf7f,0x3eca3ee6,0xbf6bbf65,0xbdb0bcc9,0xbf7fbf80,
0x3e8f3eac,0xbf76bf71,0xbe54be16,0xbf7abf7d,0x3e233e60,0xbf7dbf7a,0xbea7be89,0xbf72bf77,0x3ed23ef1,0xbf69bf62,0xbdeebd49,0xbf7ebf80,
0x3e923eb2,0xbf75bf70,0xbe7fbe3b,0xbf78bf7c,0x3e1c3e60,0xbf7dbf7a,0xbec1bea1,0xbf6dbf73,0x3c973db0,0xbf80bf7f,0xbeffbee1,0xbf5ebf66,
0x3ea13ec4,0xbf73bf6d,0xbe89be48,0xbf77bf7b,0x3e2f3e79,0xbf7cbf78,0xbecfbeac,0xbf6abf71,0x3cc93dc9,0xbf80bf7f,0xbf09bef1,0xbf58bf62,
0xbdfbbd49,0xbf7ebf80,0xbf27bf18,0xbf42bf4e,0x3e5a3e95,0xbf7abf75,0xbed2beac,0xbf69bf71,0x3d623e0a,0xbf80bf7e,0xbf0dbef7,0xbf56bf60,
0xbdd5bcc9,0xbf7fbf80,0xbf2dbf1d,0xbf3dbf4a,0xbe86be3b,0xbf77bf7c,0xbf49bf3c,0xbf1fbf2e,0x3de23e48,0xbf7ebf7b,0xbf0cbef1,0xbf57bf62,
0xbd7b3cc9,0xbf80bf80,0xbf2ebf1d,0xbf3cbf4a,0xbe6dbe16,0xbf79bf7d,0xbf4cbf3e,0xbf1bbf2c,0xbecabea1,0xbf6bbf73,0xbf63bf58,0xbeecbf09,
0x3bc93dc9,0xbf80bf7f,0xbf2bbf18,0xbf3fbf4e,0xbe35bdb0,0xbf7cbf7f,0xbf4bbf3c,0xbf1cbf2e,0xbeb5be89,0xbf6fbf77,0xbf64bf58,0xbee9bf09,
0xbf05bee1,0xbf5bbf66,0xbf75bf6e,0xbe92bebe,0xbdc90000,0xbf7fbf80,0xbf46bf35,0xbf22bf35,0xbe95be48,0xbf75bf7b,0xbf62bf55,0xbef1bf0e,
0xbef1bec4,0xbf62bf6d,0xbf75bf6d,0xbe95bec4,0xbf22bf0e,0xbf46bf55,0xbf7fbf7b,0xbdc9be48,0xbe4ebdc9,0xbf7bbf7f,0xbf5cbf4e,0xbf02bf18,
0xbecdbe9b,0xbf6bbf74,0xbf73bf69,0xbea4bed5,0xbf15befc,0xbf50bf5f,0xbf7ebf7a,0xbdeebe60,0xbf3dbf2a,0xbf2dbf40,0xbf7fbf80,0x3dbcbc49,
0xbe9bbe48,0xbf74bf7b,0xbf6ebf62,0xbebebef1,0xbf01becf,0xbf5dbf6a,0xbf7dbf77,0xbe23be89,0xbf2ebf18,0xbf3cbf4e,0xbf80bf80,0x3d7bbd49,
0xbf53bf42,0xbf11bf27,0xbf76bf7c,0x3e8f3e2f,0xbecdbe95,0xbf6bbf75,0xbf79bf71,0xbe66beac,0xbf1abf01,0xbf4dbf5d,0xbf80bf7e,0x3bc9bde2,
0xbf45bf31,0xbf24bf39,0xbf79bf7e,0x3e733dfb,0xbf65bf57,0xbee3bf0c,0xbf64bf70,0x3ee93eb2,0xbefcbec4,0xbf5fbf6d,0xbf7fbf7b,0xbd97be48,
0xbf31bf18,0xbf39bf4e,0xbf7cbf80,0x3e2f3d49,0xbf58bf46,0xbf09bf22,0xbf6abf75,0x3ecf3e95,0xbf73bf67,0xbea1bedb,0xbf4abf5c,0x3f1d3f04,
0xbf15bef1,0xbf50bf62,0xbf7fbf80,0x3da3bd49,0xbf45bf2e,0xbf24bf3c,0xbf72bf7a,0x3eaa3e54,0xbf68bf58,0xbed8bf09,0xbf54bf65,0x3f103ee6,
0xbf7cbf74,0xbe35be9b,0xbf28bf40,0x3f413f2a,0xbf2abf0e,0xbf40bf55,0xbf79bf7f,0x3e6d3dc9,0xbf57bf42,0xbf0cbf27,0xbf60bf6f,0x3ef73eb8,
0xbf74bf67,0xbe9bbedb,0xbf37bf4e,0x3f333f18,0xbf80bf7c,0xbd17be2f,0xbf01bf1d,0x3f5d3f4a,0xbf3dbf22,0xbf2dbf46,0xbf6dbf78,0x3ec13e79,
0xbf65bf53,0xbee3bf11,0xbf49bf5d,0x3f1f3f01,0xbf7cbf73,0xbe35bea1,0xbf15bf31,0x3f503f39,0xbf7fbf80,0x3dd5bd17,0xbeaabeec,0x3f723f63,
0xbf4ebf35,0xbf18bf35,0xbf5cbf6d,0x3f043ec4,0xbf71bf62,0xbeacbef1,0xbf2cbf46,0x3f3e3f22,0xbf80bf7b,0xbd49be48,0xbedbbf0e,0x3f673f55,
0xbf78bf7f,0x3e793dc9,0xbe16be95,0x3f7d3f75,0xbf5cbf46,0xbf02bf22,0xbf45bf5c,0x3f243f04,0xbf79bf6e,0xbe66bebe,0xbf0abf2a,0x3f573f40,
0xbf7fbf7f,0x3da3bd97,0xbe86becf,0x3f773f6a,0xbf6dbf79,0x3ec13e6d,0x3d30bde2,0x3f803f7e,0xbf69bf55,0xbed5bf0e,0xbf2abf46,0x3f403f22,
0xbf7ebf77,0xbde2be89,0xbecabf09,0x3f6b3f58,0xbf7abf80,0x3e543d49,0xbdb0be79,0x3f7f3f78,0xbf5dbf6f,0x3f013eb8,0x3e6d3d97,0x3f793f7f,
0xbf73bf62,0xbea4bef1,0xbf0abf2c,0x3f573f3e,0xbf80bf7d,0x3bc9be23,0xbe73beca,0x3f793f6b,0xbf72bf7c,0x3eaa3e2f,0x3dbcbd97,0x3f7f3f7f,
0xbf49bf60,0x3f1f3ef7,0x3ed23e82,0x3f693f78,0xbf7abf6d,0xbe60bec4,0xbecfbf0e,0x3f6a3f55,0xbf7ebf80,0x3dfbbd49,0xbd97be79,0x3f7f3f78,
0xbf65bf75,0x3ee63e95,0x3e893dc9,0x3f773f7f,0xbf31bf4e,0x3f393f18,0x3f133edb,0x3f513f67,0xbf7ebf75,0xbdeebe95,0xbe86bedb,0x3f773f67,
0xbf79bf80,0x3e733d7b,0x3dbcbdb0,0x3f7f3f7f,0xbf54bf6a,0x3f103ecf,0x3ede3e89,0x3f673f77,0xbf15bf37,0x3f503f33,0x3f383f16,0x3f323f4f,
0xbf80bf7b,0xbc49be48,0xbde2be95,0x3f7e3f75,0xbf70bf7c,0x3eb23e2f,0x3e823d97,0x3f783f7f,0xbf40bf5c,0x3f2a3f04,0x3f163edb,0x3f4f3f67,
0xbeecbf1d,0x3f633f4a,0x3f573f39,0x3f0c3f31,0xbf7fbf7f,0x3dbcbdc9,0x3d30be16,0x3f803f7d,0xbf64bf76,0x3ee93e8f,0x3ed23e6d,0x3f693f79,
0xbf28bf4a,0x3f413f1d,0x3f383f13,0x3f323f51,0xbeaabf01,0x3f723f5d,0x3f6d3f57,0x3ec13f0c,
};
__device__ const __align__(128) uint64_t c_inv[5120] = {
0x80003f803f003f00,0x80003f8080003f80,0x80003f8080003f80,0x80003f8080003f80,0x80003f8080003f80,0x80003f8080003f80,0x80003f8080003f80,0x80003f8080003f80,
0x80003f8080003f80,0x80003f8080003f80,0x80003f8080003f80,0x80003f8080003f80,0x80003f8080003f80,0x80003f8080003f80,0x80003f8080003f80,0x80003f8080003f80,
0x3e48bf7bbe483f7b,0x3e48bf7bbe483f7b,0x8000bf803f003f00,0x3f800000bf800000,0x3f0ebf55bf0e3f55,0x3f0ebf55bf0e3f55,0x3ec4bf6dbec43f6d,0x3ec4bf6dbec43f6d,
0x3f55bf0ebf553f0e,0x3f55bf0ebf553f0e,0x3f35bf35bf353f35,0x3f35bf35bf353f35,0x3f7bbe48bf7b3e48,0x3f7bbe48bf7b3e48,0x3f6dbec4bf6d3ec4,0x3f6dbec4bf6d3ec4,
0xbf353f35bf353f35,0xbf353f35bf353f35,0xbf6d3ec4bf6d3ec4,0xbf6d3ec4bf6d3ec4,0x80003f803f003f00,0x8000bf808000bf80,0xbec43f6dbec43f6d,0xbec43f6dbec43f6d,
0xbf35bf35bf35bf35,0xbf35bf35bf35bf35,0xbec4bf6dbec4bf6d,0xbec4bf6dbec4bf6d,0xbf800000bf800000,0xbf800000bf800000,0xbf6dbec4bf6dbec4,0xbf6dbec4bf6dbec4,
0x3f7b3e48bf7bbe48,0x3f7b3e48bf7bbe48,0x3f6dbec4bf6d3ec4,0x3f6dbec4bf6d3ec4,0x3f0ebf55bf0e3f55,0x3f0ebf55bf0e3f55,0x8000bf803f003f00,0xbf8000003f800000,
0xbf553f0e3f55bf0e,0xbf553f0e3f55bf0e,0xbec43f6d3ec4bf6d,0xbec43f6d3ec4bf6d,0x3e483f7bbe48bf7b,0x3e483f7bbe48bf7b,0x3f353f35bf35bf35,0x3f353f35bf35bf35,
0x8000bf808000bf80,0x8000bf808000bf80,0x3f35bf353f35bf35,0x3f35bf353f35bf35,0x3f8000003f800000,0x3f8000003f800000,0x3f353f353f353f35,0x3f353f353f353f35,
0x80003f803f003f00,0x80003f8080003f80,0xbf353f35bf353f35,0xbf353f35bf353f35,0xbf800000bf800000,0xbf800000bf800000,0xbf35bf35bf35bf35,0xbf35bf35bf35bf35,
0xbf7bbe483f7b3e48,0xbf7bbe483f7b3e48,0xbf353f353f35bf35,0xbf353f353f35bf35,0x3f0ebf55bf0e3f55,0x3f0ebf55bf0e3f55,0xbec4bf6d3ec43f6d,0xbec4bf6d3ec43f6d,
0x3f55bf0ebf553f0e,0x3f55bf0ebf553f0e,0x8000bf803f003f00,0x3f800000bf800000,0x3e483f7bbe48bf7b,0x3e483f7bbe48bf7b,0x3f6d3ec4bf6dbec4,0x3f6d3ec4bf6dbec4,
0xbf353f35bf353f35,0xbf353f35bf353f35,0xbf6dbec4bf6dbec4,0xbf6dbec4bf6dbec4,0x3f8000003f800000,0x3f8000003f800000,0x3ec43f6d3ec43f6d,0x3ec43f6d3ec43f6d,
0xbf35bf35bf35bf35,0xbf35bf35bf35bf35,0x3ec4bf6d3ec4bf6d,0x3ec4bf6d3ec4bf6d,0x80003f803f003f00,0x8000bf808000bf80,0xbf6d3ec4bf6d3ec4,0xbf6d3ec4bf6d3ec4,
0xbe483f7b3e48bf7b,0xbe483f7b3e48bf7b,0x3f6d3ec4bf6dbec4,0x3f6d3ec4bf6dbec4,0x3f0ebf55bf0e3f55,0x3f0ebf55bf0e3f55,0xbf35bf353f353f35,0xbf35bf353f353f35,
0xbf553f0e3f55bf0e,0xbf553f0e3f55bf0e,0x3ec43f6dbec4bf6d,0x3ec43f6dbec4bf6d,0x3f7bbe48bf7b3e48,0x3f7bbe48bf7b3e48,0x8000bf803f003f00,0xbf8000003f800000,
0xbf800000bf003f00,0xbf35bf35bf353f35,0xbf7fbdc9bdc93f7f,0x3f7f3dc93dc9bf7f,0xbf7bbe48be483f7b,0x3f7b3e483e48bf7b,0xbf75be95be953f75,0x3f753e953e95bf75,
0xbf6dbec4bec43f6d,0x3f6d3ec43ec4bf6d,0xbf62bef1bef13f62,0x3f623ef13ef1bf62,0xbf55bf0ebf0e3f55,0x3f553f0e3f0ebf55,0xbf46bf22bf223f46,0x3f463f223f22bf46,
0x3f753e95be953f75,0xbf75be953e95bf75,0x3f800000bf003f00,0xbf353f35bf35bf35,0x3f223f46bf463f22,0xbf22bf463f46bf22,0x3f553f0ebf0e3f55,0xbf55bf0e3f0ebf55,
0x3dc93f7fbf7f3dc9,0xbdc9bf7f3f7fbdc9,0x3ec43f6dbf6d3ec4,0xbec4bf6d3f6dbec4,0xbef13f62bf62bef1,0x3ef1bf623f623ef1,0xbe483f7bbf7bbe48,0x3e48bf7b3f7b3e48,
0xbf0ebf55bf553f0e,0x3f0e3f553f55bf0e,0xbdc9bf7fbf7f3dc9,0x3dc93f7f3f7fbdc9,0xbf800000bf003f00,0x3f353f353f35bf35,0xbf62bef1bef13f62,0x3f623ef13ef1bf62,
0x3f7bbe48be48bf7b,0xbf7b3e483e483f7b,0x3f753e953e95bf75,0xbf75be95be953f75,0x3ec4bf6dbf6dbec4,0xbec43f6d3f6d3ec4,0x3f46bf22bf22bf46,0xbf463f223f223f46,
0xbef13f62bf62bef1,0x3ef1bf623f623ef1,0x3e483f7bbf7b3e48,0xbe48bf7b3f7bbe48,0x3f463f22bf223f46,0xbf46bf223f22bf46,0x3f800000bf003f00,0x3f35bf353f353f35,
0x3dc9bf7f3f7f3dc9,0xbdc93f7fbf7fbdc9,0xbf0ebf553f55bf0e,0x3f0e3f55bf553f0e,0xbf75be953e95bf75,0x3f753e95be953f75,0xbf6d3ec4bec4bf6d,0x3f6dbec43ec43f6d,
0x3f6d3ec43ec4bf6d,0xbf6dbec4bec43f6d,0x3e953f753f75be95,0xbe95bf75bf753e95,0xbf0e3f553f553f0e,0x3f0ebf55bf55bf0e,0xbf7f3dc93dc93f7f,0x3f7fbdc9bdc9bf7f,
0xbf800000bf003f00,0xbf35bf35bf353f35,0xbf22bf46bf463f22,0x3f223f463f46bf22,0x3e48bf7bbf7bbe48,0xbe483f7b3f7b3e48,0x3f62bef1bef1bf62,0xbf623ef13ef13f62,
0x3f22bf463f463f22,0xbf223f46bf46bf22,0xbec4bf6d3f6dbec4,0x3ec43f6dbf6d3ec4,0x3e953f75bf753e95,0xbe95bf753f75be95,0x3f7b3e48be483f7b,0xbf7bbe483e48bf7b,
0x3ef13f62bf623ef1,0xbef1bf623f62bef1,0x3f800000bf003f00,0xbf353f35bf35bf35,0xbf7fbdc93dc9bf7f,0x3f7f3dc9bdc93f7f,0xbf0e3f55bf55bf0e,0x3f0ebf553f553f0e,
0xbe48bf7bbf7b3e48,0x3e483f7b3f7bbe48,0x3f62bef1bef1bf62,0xbf623ef13ef13f62,0xbec43f6d3f6d3ec4,0x3ec4bf6dbf6dbec4,0xbf7fbdc9bdc93f7f,0x3f7f3dc93dc9bf7f,
0x3f55bf0ebf0ebf55,0xbf553f0e3f0e3f55,0x3f463f223f22bf46,0xbf46bf22bf223f46,0xbf800000bf003f00,0x3f353f353f35bf35,0xbe95bf75bf753e95,0x3e953f753f75be95,
0xbf22bf463f46bf22,0x3f223f46bf463f22,0xbf553f0ebf0ebf55,0x3f55bf0e3f0e3f55,0x3ef13f62bf623ef1,0xbef1bf623f62bef1,0x3f6dbec43ec43f6d,0xbf6d3ec4bec4bf6d,
0xbe95bf753f75be95,0x3e953f75bf753e95,0xbf7b3e48be48bf7b,0x3f7bbe483e483f7b,0x3dc93f7fbf7f3dc9,0xbdc9bf7f3f7fbdc9,0x3f800000bf003f00,0x3f35bf353f353f35,
0x80003f803f003f00,0x80003f8080003f80,0xbf800000bf800000,0xbf800000bf800000,0x8000bf808000bf80,0x8000bf808000bf80,0x3f8000003f800000,0x3f8000003f800000,
0x80003f8080003f80,0x80003f8080003f80,0xbf800000bf800000,0xbf800000bf800000,0x8000bf808000bf80,0x8000bf808000bf80,0x3f8000003f800000,0x3f8000003f800000,
0x3f7b3e48bf7bbe48,0x3f7b3e48bf7bbe48,0x8000bf803f003f00,0x3f800000bf800000,0xbf55bf0e3f553f0e,0xbf55bf0e3f553f0e,0xbec43f6d3ec4bf6d,0xbec43f6d3ec4bf6d,
0x3f0e3f55bf0ebf55,0x3f0e3f55bf0ebf55,0x3f35bf35bf353f35,0x3f35bf35bf353f35,0xbe48bf7b3e483f7b,0xbe48bf7b3e483f7b,0xbf6d3ec43f6dbec4,0xbf6d3ec43f6dbec4,
0x3f35bf353f35bf35,0x3f35bf353f35bf35,0x3ec43f6d3ec43f6d,0x3ec43f6d3ec43f6d,0x80003f803f003f00,0x8000bf808000bf80,0xbf6dbec4bf6dbec4,0xbf6dbec4bf6dbec4,
0x3f353f353f353f35,0x3f353f353f353f35,0xbf6d3ec4bf6d3ec4,0xbf6d3ec4bf6d3ec4,0xbf800000bf800000,0xbf800000bf800000,0x3ec4bf6d3ec4bf6d,0x3ec4bf6d3ec4bf6d,
0x3e48bf7bbe483f7b,0x3e48bf7bbe483f7b,0xbf6d3ec43f6dbec4,0xbf6d3ec43f6dbec4,0x3f553f0ebf55bf0e,0x3f553f0ebf55bf0e,0x8000bf803f003f00,0xbf8000003f800000,
0x3f0e3f55bf0ebf55,0x3f0e3f55bf0ebf55,0x3ec4bf6dbec43f6d,0x3ec4bf6dbec43f6d,0xbf7b3e483f7bbe48,0xbf7b3e483f7bbe48,0x3f353f35bf35bf35,0x3f353f35bf35bf35,
0x8000bf808000bf80,0x8000bf808000bf80,0x3f353f353f353f35,0x3f353f353f353f35,0xbf800000bf800000,0xbf800000bf800000,0x3f35bf353f35bf35,0x3f35bf353f35bf35,
0x80003f803f003f00,0x80003f8080003f80,0xbf35bf35bf35bf35,0xbf35bf35bf35bf35,0x3f8000003f800000,0x3f8000003f800000,0xbf353f35bf353f35,0xbf353f35bf353f35,
0x3e48bf7bbe483f7b,0x3e48bf7bbe483f7b,0xbf353f353f35bf35,0xbf353f353f35bf35,0xbf55bf0e3f553f0e,0xbf55bf0e3f553f0e,0x3ec43f6dbec4bf6d,0x3ec43f6dbec4bf6d,
0x3f0e3f55bf0ebf55,0x3f0e3f55bf0ebf55,0x8000bf803f003f00,0x3f800000bf800000,0x3f7bbe48bf7b3e48,0x3f7bbe48bf7b3e48,0xbf6dbec43f6d3ec4,0xbf6dbec43f6d3ec4,
0x3f35bf353f35bf35,0x3f35bf353f35bf35,0xbec43f6dbec43f6d,0xbec43f6dbec43f6d,0x3f8000003f800000,0x3f8000003f800000,0xbf6d3ec4bf6d3ec4,0xbf6d3ec4bf6d3ec4,
0x3f353f353f353f35,0x3f353f353f353f35,0xbf6dbec4bf6dbec4,0xbf6dbec4bf6dbec4,0x80003f803f003f00,0x8000bf808000bf80,0xbec4bf6dbec4bf6d,0xbec4bf6dbec4bf6d,
0x3f7b3e48bf7bbe48,0x3f7b3e48bf7bbe48,0xbf6dbec43f6d3ec4,0xbf6dbec43f6d3ec4,0x3f553f0ebf55bf0e,0x3f553f0ebf55bf0e,0xbf35bf353f353f35,0xbf35bf353f353f35,
0x3f0e3f55bf0ebf55,0x3f0e3f55bf0ebf55,0xbec4bf6d3ec43f6d,0xbec4bf6d3ec43f6d,0x3e483f7bbe48bf7b,0x3e483f7bbe48bf7b,0x8000bf803f003f00,0xbf8000003f800000,
0xbf800000bf003f00,0xbf35bf35bf353f35,0x3dc9bf7fbf7fbdc9,0xbdc93f7f3f7f3dc9,0x3f7b3e483e48bf7b,0xbf7bbe48be483f7b,0xbe953f753f753e95,0x3e95bf75bf75be95,
0xbf6dbec4bec43f6d,0x3f6d3ec43ec4bf6d,0x3ef1bf62bf62bef1,0xbef13f623f623ef1,0x3f553f0e3f0ebf55,0xbf55bf0ebf0e3f55,0xbf223f463f463f22,0x3f22bf46bf46bf22,
0xbe953f75bf75be95,0x3e95bf753f753e95,0x3f800000bf003f00,0xbf353f35bf35bf35,0x3f46bf223f223f46,0xbf463f22bf22bf46,0xbf55bf0e3f0ebf55,0x3f553f0ebf0e3f55,
0xbf7f3dc9bdc9bf7f,0x3f7fbdc93dc93f7f,0x3ec43f6dbf6d3ec4,0xbec4bf6d3f6dbec4,0x3f623ef1bef13f62,0xbf62bef13ef1bf62,0x3e48bf7b3f7b3e48,0xbe483f7bbf7bbe48,
0x3f0e3f553f55bf0e,0xbf0ebf55bf553f0e,0xbf7f3dc93dc93f7f,0x3f7fbdc9bdc9bf7f,0xbf800000bf003f00,0x3f353f353f35bf35,0x3ef1bf62bf62bef1,0xbef13f623f623ef1,
0xbf7b3e483e483f7b,0x3f7bbe48be48bf7b,0x3e95bf75bf75be95,0xbe953f753f753e95,0x3ec4bf6dbf6dbec4,0xbec43f6d3f6d3ec4,0x3f223f463f46bf22,0xbf22bf46bf463f22,
0x3f623ef1bef13f62,0xbf62bef13ef1bf62,0xbe48bf7b3f7bbe48,0x3e483f7bbf7b3e48,0xbf223f46bf46bf22,0x3f22bf463f463f22,0x3f800000bf003f00,0x3f35bf353f353f35,
0xbf7fbdc93dc9bf7f,0x3f7f3dc9bdc93f7f,0x3f0e3f55bf553f0e,0xbf0ebf553f55bf0e,0x3e95bf753f753e95,0xbe953f75bf75be95,0xbf6d3ec4bec4bf6d,0x3f6dbec43ec43f6d,
0x3f6d3ec43ec4bf6d,0xbf6dbec4bec43f6d,0xbf753e953e953f75,0x3f75be95be95bf75,0x3f0ebf55bf55bf0e,0xbf0e3f553f553f0e,0x3dc93f7f3f7fbdc9,0xbdc9bf7fbf7f3dc9,
0xbf800000bf003f00,0xbf35bf35bf353f35,0x3f46bf22bf22bf46,0xbf463f223f223f46,0xbe483f7b3f7b3e48,0x3e48bf7bbf7bbe48,0xbef1bf62bf623ef1,0x3ef13f623f62bef1,
0x3f463f22bf223f46,0xbf46bf223f22bf46,0xbec4bf6d3f6dbec4,0x3ec43f6dbf6d3ec4,0x3f75be953e953f75,0xbf753e95be95bf75,0xbf7bbe483e48bf7b,0x3f7b3e48be483f7b,
0xbf623ef1bef1bf62,0x3f62bef13ef13f62,0x3f800000bf003f00,0xbf353f35bf35bf35,0xbdc93f7fbf7fbdc9,0x3dc9bf7f3f7f3dc9,0x3f0ebf553f553f0e,0xbf0e3f55bf55bf0e,
0x3e483f7b3f7bbe48,0xbe48bf7bbf7b3e48,0xbef1bf62bf623ef1,0x3ef13f623f62bef1,0xbec43f6d3f6d3ec4,0x3ec4bf6dbf6dbec4,0x3dc9bf7fbf7fbdc9,0xbdc93f7f3f7f3dc9,
0xbf553f0e3f0e3f55,0x3f55bf0ebf0ebf55,0x3f22bf46bf46bf22,0xbf223f463f463f22,0xbf800000bf003f00,0x3f353f353f35bf35,0x3f75be95be95bf75,0xbf753e953e953f75,
0xbf463f22bf22bf46,0x3f46bf223f223f46,0x3f55bf0e3f0e3f55,0xbf553f0ebf0ebf55,0xbf623ef1bef1bf62,0x3f62bef13ef13f62,0x3f6dbec43ec43f6d,0xbf6d3ec4bec4bf6d,
0xbf753e95be95bf75,0x3f75be953e953f75,0x3f7bbe483e483f7b,0xbf7b3e48be48bf7b,0xbf7f3dc9bdc9bf7f,0x3f7fbdc93dc93f7f,0x3f800000bf003f00,0x3f35bf353f353f35,
0x80003f803f003f00,0x80003f8080003f80,0x8000bf808000bf80,0x8000bf808000bf80,0x80003f8080003f80,0x80003f8080003f80,0x8000bf808000bf80,0x8000bf808000bf80,
0x80003f8080003f80,0x80003f8080003f80,0x8000bf808000bf80,0x8000bf808000bf80,0x80003f8080003f80,0x80003f8080003f80,0x8000bf808000bf80,0x8000bf808000bf80,
0xbe483f7b3e48bf7b,0xbe483f7b3e48bf7b,0x8000bf803f003f00,0x3f800000bf800000,0xbf0e3f553f0ebf55,0xbf0e3f553f0ebf55,0x3ec4bf6dbec43f6d,0x3ec4bf6dbec43f6d,
0xbf553f0e3f55bf0e,0xbf553f0e3f55bf0e,0x3f35bf35bf353f35,0x3f35bf35bf353f35,0xbf7b3e483f7bbe48,0xbf7b3e483f7bbe48,0x3f6dbec4bf6d3ec4,0x3f6dbec4bf6d3ec4,
0xbf353f35bf353f35,0xbf353f35bf353f35,0x3f6dbec43f6dbec4,0x3f6dbec43f6dbec4,0x80003f803f003f00,0x8000bf808000bf80,0x3ec4bf6d3ec4bf6d,0x3ec4bf6d3ec4bf6d,
0xbf35bf35bf35bf35,0xbf35bf35bf35bf35,0x3ec43f6d3ec43f6d,0x3ec43f6d3ec43f6d,0xbf800000bf800000,0xbf800000bf800000,0x3f6d3ec43f6d3ec4,0x3f6d3ec43f6d3ec4,
0xbf7bbe483f7b3e48,0xbf7bbe483f7b3e48,0x3f6dbec4bf6d3ec4,0x3f6dbec4bf6d3ec4,0xbf0e3f553f0ebf55,0xbf0e3f553f0ebf55,0x8000bf803f003f00,0xbf8000003f800000,
0x3f55bf0ebf553f0e,0x3f55bf0ebf553f0e,0xbec43f6d3ec4bf6d,0xbec43f6d3ec4bf6d,0xbe48bf7b3e483f7b,0xbe48bf7b3e483f7b,0x3f353f35bf35bf35,0x3f353f35bf35bf35,
0x8000bf808000bf80,0x8000bf808000bf80,0xbf353f35bf353f35,0xbf353f35bf353f35,0x3f8000003f800000,0x3f8000003f800000,0xbf35bf35bf35bf35,0xbf35bf35bf35bf35,
0x80003f803f003f00,0x80003f8080003f80,0x3f35bf353f35bf35,0x3f35bf353f35bf35,0xbf800000bf800000,0xbf800000bf800000,0x3f353f353f353f35,0x3f353f353f353f35,
0x3f7b3e48bf7bbe48,0x3f7b3e48bf7bbe48,0xbf353f353f35bf35,0xbf353f353f35bf35,0xbf0e3f553f0ebf55,0xbf0e3f553f0ebf55,0xbec4bf6d3ec43f6d,0xbec4bf6d3ec43f6d,
0xbf553f0e3f55bf0e,0xbf553f0e3f55bf0e,0x8000bf803f003f00,0x3f800000bf800000,0xbe48bf7b3e483f7b,0xbe48bf7b3e483f7b,0x3f6d3ec4bf6dbec4,0x3f6d3ec4bf6dbec4,
0xbf353f35bf353f35,0xbf353f35bf353f35,0x3f6d3ec43f6d3ec4,0x3f6d3ec43f6d3ec4,0x3f8000003f800000,0x3f8000003f800000,0xbec4bf6dbec4bf6d,0xbec4bf6dbec4bf6d,
0xbf35bf35bf35bf35,0xbf35bf35bf35bf35,0xbec43f6dbec43f6d,0xbec43f6dbec43f6d,0x80003f803f003f00,0x8000bf808000bf80,0x3f6dbec43f6dbec4,0x3f6dbec43f6dbec4,
0x3e48bf7bbe483f7b,0x3e48bf7bbe483f7b,0x3f6d3ec4bf6dbec4,0x3f6d3ec4bf6dbec4,0xbf0e3f553f0ebf55,0xbf0e3f553f0ebf55,0xbf35bf353f353f35,0xbf35bf353f353f35,
0x3f55bf0ebf553f0e,0x3f55bf0ebf553f0e,0x3ec43f6dbec4bf6d,0x3ec43f6dbec4bf6d,0xbf7b3e483f7bbe48,0xbf7b3e483f7bbe48,0x8000bf803f003f00,0xbf8000003f800000,
0xbf800000bf003f00,0xbf35bf35bf353f35,0x3f7f3dc93dc9bf7f,0xbf7fbdc9bdc93f7f,0xbf7bbe48be483f7b,0x3f7b3e483e48bf7b,0x3f753e953e95bf75,0xbf75be95be953f75,
0xbf6dbec4bec43f6d,0x3f6d3ec43ec4bf6d,0x3f623ef13ef1bf62,0xbf62bef1bef13f62,0xbf55bf0ebf0e3f55,0x3f553f0e3f0ebf55,0x3f463f223f22bf46,0xbf46bf22bf223f46,
0xbf75be953e95bf75,0x3f753e95be953f75,0x3f800000bf003f00,0xbf353f35bf35bf35,0xbf22bf463f46bf22,0x3f223f46bf463f22,0x3f553f0ebf0e3f55,0xbf55bf0e3f0ebf55,
0xbdc9bf7f3f7fbdc9,0x3dc93f7fbf7f3dc9,0x3ec43f6dbf6d3ec4,0xbec4bf6d3f6dbec4,0x3ef1bf623f623ef1,0xbef13f62bf62bef1,0xbe483f7bbf7bbe48,0x3e48bf7b3f7b3e48,
0xbf0ebf55bf553f0e,0x3f0e3f553f55bf0e,0x3dc93f7f3f7fbdc9,0xbdc9bf7fbf7f3dc9,0xbf800000bf003f00,0x3f353f353f35bf35,0x3f623ef13ef1bf62,0xbf62bef1bef13f62,
0x3f7bbe48be48bf7b,0xbf7b3e483e483f7b,0xbf75be95be953f75,0x3f753e953e95bf75,0x3ec4bf6dbf6dbec4,0xbec43f6d3f6d3ec4,0xbf463f223f223f46,0x3f46bf22bf22bf46,
0x3ef1bf623f623ef1,0xbef13f62bf62bef1,0x3e483f7bbf7b3e48,0xbe48bf7b3f7bbe48,0xbf46bf223f22bf46,0x3f463f22bf223f46,0x3f800000bf003f00,0x3f35bf353f353f35,
0xbdc93f7fbf7fbdc9,0x3dc9bf7f3f7f3dc9,0xbf0ebf553f55bf0e,0x3f0e3f55bf553f0e,0x3f753e95be953f75,0xbf75be953e95bf75,0xbf6d3ec4bec4bf6d,0x3f6dbec43ec43f6d,
0x3f6d3ec43ec4bf6d,0xbf6dbec4bec43f6d,0xbe95bf75bf753e95,0x3e953f753f75be95,0xbf0e3f553f553f0e,0x3f0ebf55bf55bf0e,0x3f7fbdc9bdc9bf7f,0xbf7f3dc93dc93f7f,
0xbf800000bf003f00,0xbf35bf35bf353f35,0x3f223f463f46bf22,0xbf22bf46bf463f22,0x3e48bf7bbf7bbe48,0xbe483f7b3f7b3e48,0xbf623ef13ef13f62,0x3f62bef1bef1bf62,
0xbf223f46bf46bf22,0x3f22bf463f463f22,0xbec4bf6d3f6dbec4,0x3ec43f6dbf6d3ec4,0xbe95bf753f75be95,0x3e953f75bf753e95,0x3f7b3e48be483f7b,0xbf7bbe483e48bf7b,
0xbef1bf623f62bef1,0x3ef13f62bf623ef1,0x3f800000bf003f00,0xbf353f35bf35bf35,0x3f7f3dc9bdc93f7f,0xbf7fbdc93dc9bf7f,0xbf0e3f55bf55bf0e,0x3f0ebf553f553f0e,
0xbe48bf7bbf7b3e48,0x3e483f7b3f7bbe48,0xbf623ef13ef13f62,0x3f62bef1bef1bf62,0xbec43f6d3f6d3ec4,0x3ec4bf6dbf6dbec4,0x3f7f3dc93dc9bf7f,0xbf7fbdc9bdc93f7f,
0x3f55bf0ebf0ebf55,0xbf553f0e3f0e3f55,0xbf46bf22bf223f46,0x3f463f223f22bf46,0xbf800000bf003f00,0x3f353f353f35bf35,0x3e953f753f75be95,0xbe95bf75bf753e95,
0x3f223f46bf463f22,0xbf22bf463f46bf22,0xbf553f0ebf0ebf55,0x3f55bf0e3f0e3f55,0xbef1bf623f62bef1,0x3ef13f62bf623ef1,0x3f6dbec43ec43f6d,0xbf6d3ec4bec4bf6d,
0x3e953f75bf753e95,0xbe95bf753f75be95,0xbf7b3e48be48bf7b,0x3f7bbe483e483f7b,0xbdc9bf7f3f7fbdc9,0x3dc93f7fbf7f3dc9,0x3f800000bf003f00,0x3f35bf353f353f35,
0x80003f803f003f00,0x80003f8080003f80,0x3f8000003f800000,0x3f8000003f800000,0x8000bf808000bf80,0x8000bf808000bf80,0xbf800000bf800000,0xbf800000bf800000,
0x80003f8080003f80,0x80003f8080003f80,0x3f8000003f800000,0x3f8000003f800000,0x8000bf808000bf80,0x8000bf808000bf80,0xbf800000bf800000,0xbf800000bf800000,
0xbf7bbe483f7b3e48,0xbf7bbe483f7b3e48,0x8000bf803f003f00,0x3f800000bf800000,0x3f553f0ebf55bf0e,0x3f553f0ebf55bf0e,0xbec43f6d3ec4bf6d,0xbec43f6d3ec4bf6d,
0xbf0ebf553f0e3f55,0xbf0ebf553f0e3f55,0x3f35bf35bf353f35,0x3f35bf35bf353f35,0x3e483f7bbe48bf7b,0x3e483f7bbe48bf7b,0xbf6d3ec43f6dbec4,0xbf6d3ec43f6dbec4,
0x3f35bf353f35bf35,0x3f35bf353f35bf35,0xbec4bf6dbec4bf6d,0xbec4bf6dbec4bf6d,0x80003f803f003f00,0x8000bf808000bf80,0x3f6d3ec43f6d3ec4,0x3f6d3ec43f6d3ec4,
0x3f353f353f353f35,0x3f353f353f353f35,0x3f6dbec43f6dbec4,0x3f6dbec43f6dbec4,0xbf800000bf800000,0xbf800000bf800000,0xbec43f6dbec43f6d,0xbec43f6dbec43f6d,
0xbe483f7b3e48bf7b,0xbe483f7b3e48bf7b,0xbf6d3ec43f6dbec4,0xbf6d3ec43f6dbec4,0xbf55bf0e3f553f0e,0xbf55bf0e3f553f0e,0x8000bf803f003f00,0xbf8000003f800000,
0xbf0ebf553f0e3f55,0xbf0ebf553f0e3f55,0x3ec4bf6dbec43f6d,0x3ec4bf6dbec43f6d,0x3f7bbe48bf7b3e48,0x3f7bbe48bf7b3e48,0x3f353f35bf35bf35,0x3f353f35bf35bf35,
0x8000bf808000bf80,0x8000bf808000bf80,0xbf35bf35bf35bf35,0xbf35bf35bf35bf35,0xbf800000bf800000,0xbf800000bf800000,0xbf353f35bf353f35,0xbf353f35bf353f35,
0x80003f803f003f00,0x80003f8080003f80,0x3f353f353f353f35,0x3f353f353f353f35,0x3f8000003f800000,0x3f8000003f800000,0x3f35bf353f35bf35,0x3f35bf353f35bf35,
0xbe483f7b3e48bf7b,0xbe483f7b3e48bf7b,0xbf353f353f35bf35,0xbf353f353f35bf35,0x3f553f0ebf55bf0e,0x3f553f0ebf55bf0e,0x3ec43f6dbec4bf6d,0x3ec43f6dbec4bf6d,
0xbf0ebf553f0e3f55,0xbf0ebf553f0e3f55,0x8000bf803f003f00,0x3f800000bf800000,0xbf7b3e483f7bbe48,0xbf7b3e483f7bbe48,0xbf6dbec43f6d3ec4,0xbf6dbec43f6d3ec4,
0x3f35bf353f35bf35,0x3f35bf353f35bf35,0x3ec4bf6d3ec4bf6d,0x3ec4bf6d3ec4bf6d,0x3f8000003f800000,0x3f8000003f800000,0x3f6dbec43f6dbec4,0x3f6dbec43f6dbec4,
0x3f353f353f353f35,0x3f353f353f353f35,0x3f6d3ec43f6d3ec4,0x3f6d3ec43f6d3ec4,0x80003f803f003f00,0x8000bf808000bf80,0x3ec43f6d3ec43f6d,0x3ec43f6d3ec43f6d,
0xbf7bbe483f7b3e48,0xbf7bbe483f7b3e48,0xbf6dbec43f6d3ec4,0xbf6dbec43f6d3ec4,0xbf55bf0e3f553f0e,0xbf55bf0e3f553f0e,0xbf35bf353f353f35,0xbf35bf353f353f35,
0xbf0ebf553f0e3f55,0xbf0ebf553f0e3f55,0xbec4bf6d3ec43f6d,0xbec4bf6d3ec43f6d,0xbe48bf7b3e483f7b,0xbe48bf7b3e483f7b,0x8000bf803f003f00,0xbf8000003f800000,
0xbf800000bf003f00,0xbf35bf35bf353f35,0xbdc93f7f3f7f3dc9,0x3dc9bf7fbf7fbdc9,0x3f7b3e483e48bf7b,0xbf7bbe48be483f7b,0x3e95bf75bf75be95,0xbe953f753f753e95,
0xbf6dbec4bec43f6d,0x3f6d3ec43ec4bf6d,0xbef13f623f623ef1,0x3ef1bf62bf62bef1,0x3f553f0e3f0ebf55,0xbf55bf0ebf0e3f55,0x3f22bf46bf46bf22,0xbf223f463f463f22,
0x3e95bf753f753e95,0xbe953f75bf75be95,0x3f800000bf003f00,0xbf353f35bf35bf35,0xbf463f22bf22bf46,0x3f46bf223f223f46,0xbf55bf0e3f0ebf55,0x3f553f0ebf0e3f55,
0x3f7fbdc93dc93f7f,0xbf7f3dc9bdc9bf7f,0x3ec43f6dbf6d3ec4,0xbec4bf6d3f6dbec4,0xbf62bef13ef1bf62,0x3f623ef1bef13f62,0x3e48bf7b3f7b3e48,0xbe483f7bbf7bbe48,
0x3f0e3f553f55bf0e,0xbf0ebf55bf553f0e,0x3f7fbdc9bdc9bf7f,0xbf7f3dc93dc93f7f,0xbf800000bf003f00,0x3f353f353f35bf35,0xbef13f623f623ef1,0x3ef1bf62bf62bef1,
0xbf7b3e483e483f7b,0x3f7bbe48be48bf7b,0xbe953f753f753e95,0x3e95bf75bf75be95,0x3ec4bf6dbf6dbec4,0xbec43f6d3f6d3ec4,0xbf22bf46bf463f22,0x3f223f463f46bf22,
0xbf62bef13ef1bf62,0x3f623ef1bef13f62,0xbe48bf7b3f7bbe48,0x3e483f7bbf7b3e48,0x3f22bf463f463f22,0xbf223f46bf46bf22,0x3f800000bf003f00,0x3f35bf353f353f35,
0x3f7f3dc9bdc93f7f,0xbf7fbdc93dc9bf7f,0x3f0e3f55bf553f0e,0xbf0ebf553f55bf0e,0xbe953f75bf75be95,0x3e95bf753f753e95,0xbf6d3ec4bec4bf6d,0x3f6dbec43ec43f6d,
0x3f6d3ec43ec4bf6d,0xbf6dbec4bec43f6d,0x3f75be95be95bf75,0xbf753e953e953f75,0x3f0ebf55bf55bf0e,0xbf0e3f553f553f0e,0xbdc9bf7fbf7f3dc9,0x3dc93f7f3f7fbdc9,
0xbf800000bf003f00,0xbf35bf35bf353f35,0xbf463f223f223f46,0x3f46bf22bf22bf46,0xbe483f7b3f7b3e48,0x3e48bf7bbf7bbe48,0x3ef13f623f62bef1,0xbef1bf62bf623ef1,
0xbf46bf223f22bf46,0x3f463f22bf223f46,0xbec4bf6d3f6dbec4,0x3ec43f6dbf6d3ec4,0xbf753e95be95bf75,0x3f75be953e953f75,0xbf7bbe483e48bf7b,0x3f7b3e48be483f7b,
0x3f62bef13ef13f62,0xbf623ef1bef1bf62,0x3f800000bf003f00,0xbf353f35bf35bf35,0x3dc9bf7f3f7f3dc9,0xbdc93f7fbf7fbdc9,0x3f0ebf553f553f0e,0xbf0e3f55bf55bf0e,
0x3e483f7b3f7bbe48,0xbe48bf7bbf7b3e48,0x3ef13f623f62bef1,0xbef1bf62bf623ef1,0xbec43f6d3f6d3ec4,0x3ec4bf6dbf6dbec4,0xbdc93f7f3f7f3dc9,0x3dc9bf7fbf7fbdc9,
0xbf553f0e3f0e3f55,0x3f55bf0ebf0ebf55,0xbf223f463f463f22,0x3f22bf46bf46bf22,0xbf800000bf003f00,0x3f353f353f35bf35,0xbf753e953e953f75,0x3f75be95be95bf75,
0x3f46bf223f223f46,0xbf463f22bf22bf46,0x3f55bf0e3f0e3f55,0xbf553f0ebf0ebf55,0x3f62bef13ef13f62,0xbf623ef1bef1bf62,0x3f6dbec43ec43f6d,0xbf6d3ec4bec4bf6d,
0x3f75be953e953f75,0xbf753e95be95bf75,0x3f7bbe483e483f7b,0xbf7b3e48be48bf7b,0x3f7fbdc93dc93f7f,0xbf7f3dc9bdc9bf7f,0x3f800000bf003f00,0x3f35bf353f353f35,
0x80003f8080003f80,0xbec43f6d80003f80,0x80003f8080003f80,0xbf6dbec480003f80,0x80003f8080003f80,0x3ec4bf6d80003f80,0x80003f8080003f80,0x3f6d3ec480003f80,
0x80003f8080003f80,0xbec43f6d80003f80,0x80003f8080003f80,0xbf6dbec480003f80,0x80003f8080003f80,0x3ec4bf6d80003f80,0x80003f8080003f80,0x3f6d3ec480003f80,
0xbe953f75be793f78,0xbf4ebf18beac3f71,0xbdc93f7fbd493f80,0xbedb3f67be163f7d,0xbf223f46bf183f4e,0x3f043f5cbf2c3f3e,0xbef13f62bedb3f67,0x3f3ebf2cbf043f5c,
0xbf623ef1bf5c3f04,0xbe16bf7dbf673edb,0xbf463f22bf3e3f2c,0xbf713eacbf4e3f18,0xbf7f3dc9bf7d3e16,0xbe793f78bf803d49,0xbf753e95bf713eac,0x3f803d49bf783e79,
0xbf553f0ebf463f22,0x3f75be95bf623ef1,0xbf7b3e48bf753e95,0xbdc93f7fbf7f3dc9,0xbe483f7bbdc93f7f,0xbef13f62be953f75,0xbf0e3f55bef13f62,0xbf22bf46bf223f46,
0xbf0ebf55bf22bf46,0x3e953f75bef1bf62,0xbe48bf7bbe95bf75,0xbf7fbdc9bdc9bf7f,0xbf7bbe48bf7fbdc9,0xbf62bef1bf75be95,0xbf55bf0ebf62bef1,0x3f46bf22bf46bf22,
0xbf62bef1bf71beac,0xbf2c3f3ebf4ebf18,0xbf7f3dc9bf783e79,0x3f7d3e16bf80bd49,0xbf463f22bf2c3f3e,0xbedbbf67bf5c3f04,0xbe953f75be163f7d,0xbf043f5cbedb3f67,
0x3f75be953f67bedb,0xbd49bf803f7dbe16,0x3f22bf463f04bf5c,0xbf4e3f183f3ebf2c,0x3dc9bf7fbd49bf80,0x3f713eac3e79bf78,0xbef1bf62bf18bf4e,0xbe79bf78beacbf71,
0x3ec4bf6d3e48bf7b,0x3f0ebf553f0ebf55,0x3f6dbec43f55bf0e,0x3e483f7b3f7bbe48,0x3f6d3ec43f7b3e48,0xbf55bf0e3f553f0e,0x3ec43f6d3f0e3f55,0x3f7bbe483e483f7b,
0xbec43f6dbe483f7b,0xbf0e3f55bf0e3f55,0xbf6d3ec4bf553f0e,0xbe48bf7bbf7b3e48,0xbf6dbec4bf7bbe48,0x3f553f0ebf55bf0e,0xbec4bf6dbf0ebf55,0xbf7b3e48be48bf7b,
0x3f463f223f673edb,0xbf3e3f2c3f183f4e,0x3f75be953f5cbf04,0x3f7dbe163f80bd49,0xbf623ef1bf3e3f2c,0x3eac3f71bf783e79,0xbdc93f7f3e163f7d,0x3e79bf78beac3f71,
0xbf7f3dc9bf713eac,0x3d49bf80bf7dbe16,0xbef13f62be793f78,0xbf183f4ebf2c3f3e,0x3e95bf753d49bf80,0xbf67bedb3f04bf5c,0xbf22bf46bf4ebf18,0x3f043f5cbedbbf67,
0xbf7b3e48bf623ef1,0x3f7fbdc9bf7fbdc9,0xbf0ebf55bf46bf22,0xbf623ef1be95bf75,0x3f553f0e3f753e95,0x3f463f223f223f46,0xbe483f7b3dc93f7f,0xbf75be95bef13f62,
0xbe48bf7bbef1bf62,0x3dc93f7f3dc9bf7f,0x3f55bf0e3f22bf46,0xbef1bf623f75be95,0xbf0e3f55be953f75,0xbf223f46bf463f22,0xbf7bbe48bf7f3dc9,0x3e95bf75bf62bef1,
0x3f46bf223f04bf5c,0xbf18bf4e3f71beac,0xbef1bf62bf3ebf2c,0x3edb3f67be16bf7d,0xbf753e95bf4e3f18,0xbe79bf78bf80bd49,0x3dc93f7f3edb3f67,0x3d493f80be793f78,
0x3f7f3dc93f78be79,0x3e16bf7d3f673edb,0x3e95bf75bd49bf80,0xbeac3f713f18bf4e,0xbf62bef1bf7dbe16,0x3f04bf5cbf2cbf3e,0xbf223f46beac3f71,0xbf2c3f3ebf5c3f04,
0xbd493f80bcc93f80,0xbecf3f6abd973f7f,0xbe163f7dbdfb3f7e,0xbf5fbefcbe2f3f7c,0xbe793f78be603f7a,0x3f13bf51be893f77,0xbeac3f71bea13f73,0x3f423f27beb83f6f,
0xbedb3f67becf3f6a,0xbf393f31bee63f65,0xbf043f5cbefc3f5f,0xbf1dbf4abf093f58,0xbf183f4ebf133f51,0x3f58bf09bf1d3f4a,0xbf2c3f3ebf273f42,0x3ee63f65bf313f39,
0xbedb3f67beb83f6f,0xbf39bf31befc3f5f,0xbe163f7dbd973f7f,0xbee63f65be603f7a,0xbf5c3f04bf513f13,0x3e603f7abf653ee6,0xbf2c3f3ebf1d3f4a,0x3f5fbefcbf393f31,
0xbf80bd49bf803cc9,0x3eb8bf6fbf7ebdfb,0xbf783e79bf733ea1,0xbf7fbd97bf7c3e2f,0xbf4ebf18bf58bf09,0xbf513f13bf42bf27,0xbf71beacbf77be89,0x3f4a3f1dbf6abecf,
0xbf713eacbf653ee6,0x3f7fbd97bf7a3e60,0xbf7dbe16bf80bcc9,0xbecf3f6abf77be89,0xbe793f78bdfb3f7e,0xbefc3f5fbeb83f6f,0xbf2c3f3ebf133f51,0xbf09bf58bf423f27,
0x3d49bf80bd97bf7f,0xbea13f733e2fbf7c,0x3f04bf5c3ecfbf6a,0xbf31bf393f1dbf4a,0xbf4ebf18bf5fbefc,0xbf1dbf4abf39bf31,0xbedbbf67bf09bf58,0x3f7cbe2fbea1bf73,
0xbf2cbf3ebf4abf1d,0xbf5f3efcbf09bf58,0xbf7dbe16bf803cc9,0x3f6f3eb8bf73bea1,0xbf5c3f04bf423f27,0xbea1bf73bf6f3eb8,0xbeac3f71be2f3f7c,0xbf093f58befc3f5f,
0x3f673edb3f773e89,0x3f1dbf4a3f513f13,0x3f78be793f6abecf,0xbf803cc93f7fbd97,0x3f18bf4e3ee6bf65,0x3f273f423f39bf31,0xbd49bf80be60bf7a,0x3e2fbf7c3dfbbf7e,
0x3f3ebf2c3f13bf51,0x3f58bf093f5fbefc,0x3f7d3e163f7fbd97,0xbea13f733f6f3eb8,0x3f043f5c3f313f39,0xbeb8bf6f3ea13f73,0xbeac3f71bdfb3f7e,0x3f5f3efcbf093f58,
0xbedb3f67be603f7a,0xbf133f51bf1d3f4a,0xbf783e79bf653ee6,0xbd97bf7fbf803cc9,0xbf4ebf18bf6abecf,0x3f313f39bf27bf42,0xbd49bf80be89bf77,0xbf7ebdfb3e2fbf7c,
0x3eac3f713f133f51,0xbf7a3e603d973f7f,0x3f7d3e163f7ebdfb,0x3f773e893f6a3ecf,0xbf78be79bf803cc9,0xbeb83f6fbf5fbefc,0xbf2c3f3ebee63f65,0x3f42bf27bf583f09,
0xbf80bd49bf7a3e60,0x3e2fbf7cbf73bea1,0xbf043f5cbe893f77,0xbf1d3f4abf393f31,0x3f18bf4e3eb8bf6f,0xbf39bf313f4abf1d,0xbedbbf67bf27bf42,0x3ea13f73be2fbf7c,
0xbf67bedbbf7ebdfb,0x3f5f3efcbf39bf31,0x3e16bf7dbe2fbf7c,0xbf7abe603ee6bf65,0x3f043f5c3f423f27,0x3ee63f653e603f7a,0xbf2c3f3ebecf3f6a,0xbf31bf39bf5f3efc,
0x3d49bf80be89bf77,0xbdfb3f7e3eb8bf6f,0x3f78be793f58bf09,0xbe2fbf7c3f7f3d97,0xbf183f4ebea13f73,0xbf273f42bf513f13,0xbf71beacbf80bcc9,0x3ecfbf6abf4abf1d,
0x3f803d493f73bea1,0x3d97bf7f3f6a3ecf,0x3e16bf7dbe60bf7a,0xbe2f3f7c3efcbf5f,0xbf78be79bf7e3dfb,0x3e89bf77bf51bf13,0xbeac3f713cc93f80,0xbeb83f6fbf273f42,
0x3f673edb3f7f3d97,0x3ee6bf653f313f39,0x3f04bf5c3e2fbf7c,0xbf093f583f4abf1d,0xbf4ebf18bf77be89,0x3f1dbf4abf09bf58,0xbf2c3f3ebeb83f6f,0xbf313f39bf653ee6,
0xbf6d3ec4bf353f35,0xbf800000bf353f35,0xbec4bf6dbf35bf35,0x3f8000003f35bf35,0x3f6dbec43f35bf35,0xbf800000bf353f35,0x3ec43f6d3f353f35,0x3f8000003f35bf35,
0xbf6d3ec4bf353f35,0xbf800000bf353f35,0xbec4bf6dbf35bf35,0x3f8000003f35bf35,0x3f6dbec43f35bf35,0xbf800000bf353f35,0x3ec43f6d3f353f35,0x3f8000003f35bf35,
0xbd49bf80bef1bf62,0x3f753e953f5cbf04,0xbf783e79bf463f22,0xbf7fbdc9bf3e3f2c,0xbeac3f713dc93f7f,0x3f463f223f7dbe16,0x3f7d3e163f75be95,0xbf62bef1bf713eac,
0x3f2cbf3e3e95bf75,0x3ef13f623f783e79,0xbf5cbf04bf7fbdc9,0xbf22bf46bf80bd49,0xbf673edbbf223f46,0x3dc93f7f3f4e3f18,0x3f183f4e3f623ef1,0xbe95bf75bf67bedb,
0x3f463f223f7b3e48,0xbf0ebf55bf7fbdc9,0xbf623ef1bf0e3f55,0x3e483f7b3f623ef1,0xbf7f3dc9bf553f0e,0xbf7bbe48bf463f22,0x3e95bf75be48bf7b,0x3f553f0e3f75be95,
0xbf223f46be483f7b,0x3f55bf0e3dc9bf7f,0xbef1bf62bf55bf0e,0xbf7b3e48bef13f62,0xbdc9bf7fbf0ebf55,0x3e48bf7bbf22bf46,0x3f753e953f7bbe48,0xbf0e3f553e953f75,
0xbf78be79bf753e95,0xbef13f623edb3f67,0x3eac3f713f463f22,0xbdc9bf7fbf5cbf04,0x3f18bf4e3dc9bf7f,0x3f223f463f80bd49,0xbf80bd49bf623ef1,0xbf75be95bf4e3f18,
0x3f5cbf043ef1bf62,0xbe95bf75bf71beac,0xbf67bedbbf7f3dc9,0x3f463f223f78be79,0x3e163f7d3f223f46,0xbf7fbdc9bf2c3f3e,0x3f3ebf2c3e95bf75,0x3f62bef13e16bf7d,
0x3f7b3e483f6dbec4,0x3f6d3ec43f55bf0e,0xbf553f0ebec43f6d,0xbec4bf6dbf7bbe48,0x3e48bf7bbec4bf6d,0xbec43f6d3f0e3f55,0x3f0e3f553f6d3ec4,0x3f6dbec43e48bf7b,
0xbf7bbe48bf6d3ec4,0xbf6dbec4bf553f0e,0x3f55bf0e3ec4bf6d,0x3ec43f6d3f7b3e48,0xbe483f7b3ec43f6d,0x3ec4bf6dbf0ebf55,0xbf0ebf55bf6dbec4,0xbf6d3ec4be483f7b,
0xbf5cbf04bf7f3dc9,0x3f22bf46beacbf71,0x3edb3f673f623ef1,0x3e953f753f783e79,0xbf4e3f18be953f75,0x3ef13f623f803d49,0x3f80bd493f46bf22,0xbf7fbdc9bf183f4e,
0x3f78be793f22bf46,0x3dc93f7f3f673edb,0xbf71beacbf753e95,0xbf62bef1bf5c3f04,0x3e16bf7dbef1bf62,0xbf75be95bf3e3f2c,0xbf2c3f3ebdc93f7f,0x3f46bf22be16bf7d,
0x3e953f753f553f0e,0xbe48bf7bbf75be95,0xbf22bf46bf7bbe48,0xbf553f0e3dc93f7f,0xbef13f623e483f7b,0xbf0e3f553ef13f62,0x3dc9bf7fbf0ebf55,0x3f7b3e483f22bf46,
0xbf753e95bf0e3f55,0x3f7bbe483e95bf75,0x3f46bf223e48bf7b,0xbf0ebf55bf7f3dc9,0xbf62bef1bf7b3e48,0xbf55bf0ebf623ef1,0x3f7f3dc93f55bf0e,0xbe483f7b3f463f22,
0x3f3ebf2c3dc9bf7f,0xbf22bf46bf783e79,0xbf5c3f04be953f75,0x3f62bef1bd49bf80,0x3f71beac3ef1bf62,0x3e953f753f7d3e16,0xbf7d3e16bf223f46,0xbf7f3dc9beac3f71,
0x3f803d493f46bf22,0x3dc9bf7fbf5cbf04,0xbf78be79bf623ef1,0x3f753e953f2cbf3e,0x3f673edb3f75be95,0xbef13f623f183f4e,0xbf4ebf18bf7f3dc9,0xbf46bf22bf673edb,
0xbf733ea1bf3e3f2c,0xbf80bd49bf393f31,0xbe60bf7abf18bf4e,0x3f7d3e163f4abf1d,0x3f7ebdfb3f5cbf04,0xbf78be79bf583f09,0x3cc93f803edb3f67,0x3f713eac3f65bee6,
0xbf7fbd97bf713eac,0xbf67bedbbf6f3eb8,0x3e2fbf7cbe79bf78,0x3f5c3f043f77be89,0x3f773e893f7dbe16,0xbf4ebf18bf7c3e2f,0xbeb83f6f3d493f80,0x3f3e3f2c3f7fbd97,
0x3dfbbf7ebeacbf71,0x3f673edb3f6abecf,0xbf7c3e2fbf4e3f18,0xbf7dbe16bf423f27,0xbf273f42be793f78,0x3f043f5c3f7c3e2f,0x3f6a3ecf3f80bd49,0xbf3ebf2cbf7e3dfb,
0x3f77be893f3ebf2c,0xbd493f803f393f31,0xbf09bf58bf5cbf04,0xbe79bf78bf65bee6,0xbf73bea1bf7d3e16,0xbf183f4e3e603f7a,0xbcc93f803edb3f67,0x3eacbf71befcbf5f,
0x3f133f513f673edb,0xbeacbf71bf73bea1,0xbf7e3dfbbf4e3f18,0xbe163f7d3f313f39,0xbf803cc9bf5c3f04,0xbf78be79bf4a3f1d,0x3ee6bf65bd49bf80,0x3f3e3f2c3f7cbe2f,
0xbf7a3e60bf3e3f2c,0x3f803d493f27bf42,0x3e89bf77be79bf78,0xbf5cbf04bf6f3eb8,0x3eb8bf6fbe16bf7d,0x3f18bf4ebe89bf77,0x3f273f423f713eac,0xbf673edbbe603f7a,
0xbf51bf13bf80bd49,0xbf3e3f2c3dfb3f7e,0x3d973f7f3f183f4e,0x3e16bf7dbf39bf31,0x3f39bf313e79bf78,0x3f043f5c3f7f3d97,0xbf7ebdfbbf673edb,0xbf71beacbf513f13,
0x3f7a3e603f71beac,0x3edbbf67befcbf5f,0xbee6bf65bf5cbf04,0x3e793f783f6f3eb8,0xbecf3f6a3e163f7d,0xbf4ebf18bf733ea1,0x3f77be893f2cbf3e,0x3f80bd493f09bf58,
0x3f4a3f1d3f803d49,0x3f2c3f3e3f7cbe2f,0xbf803cc9bf4e3f18,0x3e16bf7dbf42bf27,0x3f42bf273e79bf78,0xbf5c3f04bcc93f80,0xbe2f3f7c3edb3f67,0x3f713eac3f4abf1d,
0xbf77be89bf713eac,0xbf67bedbbf583f09,0x3f6abecf3f04bf5c,0x3e793f783f733ea1,0xbee63f653e163f7d,0x3f18bf4ebeb8bf6f,0xbe60bf7abf3ebf2c,0xbf803d49befc3f5f,
0xbee6bf65bf67bedb,0x3f71beac3e2fbf7c,0xbcc93f803f183f4e,0xbe163f7d3f4a3f1d,0xbf7ebdfbbf5c3f04,0xbe793f783f393f31,0x3f513f133f80bd49,0xbf3ebf2cbf733ea1,
0x3f7fbd973f3ebf2c,0xbd493f803f583f09,0xbf6abecfbf783e79,0xbf5cbf04bf5f3efc,0x3efcbf5fbe16bf7d,0xbf4ebf18bf6a3ecf,0xbf583f09beac3f71,0x3f67bedb3d97bf7f,
0xbeb83f6f3eac3f71,0x3edbbf67bf1dbf4a,0x3d97bf7fbf18bf4e,0xbf7dbe16bf133f51,0xbf513f13be793f78,0xbf5c3f043d973f7f,0x3f1dbf4abd49bf80,0x3f3e3f2c3f6fbeb8,
0xbf803cc9bf3e3f2c,0x3f803d493efcbf5f,0x3f73bea13f04bf5c,0xbe79bf78bf7abe60,0xbf58bf09bf7d3e16,0xbf4ebf18bf653ee6,0x3f773e893f67bedb,0xbeac3f713f313f39,
0x3f803cc93f3ebf2c,0x3d49bf80bf65bee6,0xbf7ebdfbbf4e3f18,0x3f7d3e163f09bf58,0x3f7a3e603f5cbf04,0xbe793f783f4a3f1d,0xbf73bea1bf673edb,0xbf71beacbf313f39,
0x3f6a3ecf3f71beac,0x3edbbf67bf27bf42,0xbf5fbefcbf783e79,0x3f5c3f043f51bf13,0x3f513f133f7dbe16,0xbf183f4e3efc3f5f,0xbf42bf27bf803d49,0xbf3ebf2cbf6a3ecf,
0xbf6d3ec4bf35bf35,0x3ec4bf6dbf35bf35,0x3ec43f6d3f353f35,0xbf6dbec4bf353f35,0x3f6dbec4bf35bf35,0xbec43f6d3f353f35,0xbec4bf6d3f353f35,0x3f6d3ec43f35bf35,
0xbf6d3ec4bf35bf35,0x3ec4bf6dbf35bf35,0x3ec43f6d3f353f35,0xbf6dbec4bf353f35,0x3f6dbec4bf35bf35,0xbec43f6d3f353f35,0xbec4bf6d3f353f35,0x3f6d3ec43f35bf35,
0x3e163f7d3edb3f67,0xbf3ebf2cbf623ef1,0xbf713eacbf18bf4e,0x3f04bf5cbf22bf46,0x3e79bf783d493f80,0x3edb3f673f7fbdc9,0x3f803d49be79bf78,0xbf4e3f183e953f75,
0xbf183f4ebeac3f71,0xbd49bf80bf75be95,0xbf67bedb3e16bf7d,0x3f78be793dc9bf7f,0x3f5cbf04bf2c3f3e,0xbeac3f713f463f22,0x3f2c3f3e3f04bf5c,0xbf7dbe16bef13f62,
0x3f623ef13e95bf75,0xbf7f3dc9be483f7b,0x3f46bf22bf223f46,0xbe953f753f553f0e,0xbf753e95bef1bf62,0x3f22bf46bf0ebf55,0xbdc93f7f3dc93f7f,0xbef1bf62bf7b3e48,
0xbef13f623f753e95,0xbdc9bf7fbf7bbe48,0x3f223f46bf46bf22,0xbf75be95bf0e3f55,0xbe95bf753f62bef1,0x3f463f223f55bf0e,0xbf7fbdc9bf7f3dc9,0x3f62bef1be48bf7b,
0x3f80bd49bf7d3e16,0xbf5c3f043e953f75,0x3f183f4e3f3ebf2c,0xbf67bedbbf223f46,0xbeac3f71be793f78,0xbe16bf7dbf7fbdc9,0xbf783e79beacbf71,0x3f3ebf2cbef1bf62,
0xbf2c3f3e3f18bf4e,0x3e79bf78bf62bef1,0xbf7dbe16bd493f80,0x3f71beacbdc9bf7f,0xbedbbf67bf04bf5c,0x3f4e3f183f46bf22,0x3f04bf5c3f673edb,0xbd493f803f753e95,
0x3f7bbe483e483f7b,0xbf553f0e3ec43f6d,0x3f0ebf553f0ebf55,0xbe483f7b3f6d3ec4,0xbe48bf7bbf7b3e48,0x3f0e3f553f6dbec4,0xbf55bf0e3f553f0e,0x3f7b3e483ec4bf6d,
0xbf7b3e48be48bf7b,0x3f55bf0ebec4bf6d,0xbf0e3f55bf0e3f55,0x3e48bf7bbf6dbec4,0x3e483f7b3f7bbe48,0xbf0ebf55bf6d3ec4,0x3f553f0ebf55bf0e,0xbf7bbe48bec43f6d,
0x3f803d493f7d3e16,0xbf783e793dc93f7f,0x3f4e3f18bf2c3f3e,0xbf71beacbef13f62,0x3edbbf67bf043f5c,0xbe163f7d3f753e95,0x3f5cbf04bedbbf67,0xbf2c3f3e3f223f46,
0xbf3e3f2cbf4e3f18,0x3f04bf5cbf46bf22,0xbf7d3e16bd49bf80,0x3f67bedbbe95bf75,0x3eac3f71be79bf78,0xbf18bf4ebf623ef1,0xbe793f783f713eac,0xbd49bf80bf7fbdc9,
0x3f463f223f46bf22,0xbf62bef1bf0e3f55,0x3f753e95bf62bef1,0xbf7fbdc9be483f7b,0x3dc93f7fbf7fbdc9,0xbe95bf75bf7b3e48,0x3ef13f623e953f75,0xbf22bf46bf553f0e,
0xbf223f463f223f46,0x3ef1bf62bf55bf0e,0xbe953f753ef1bf62,0x3dc9bf7fbf7bbe48,0xbf7f3dc93dc9bf7f,0x3f75be95be48bf7b,0xbf623ef1bf753e95,0x3f46bf22bf0ebf55,
0xbe163f7d3edbbf67,0x3d49bf80bf7fbdc9,0xbeac3f713f4e3f18,0x3e79bf78bf75be95,0xbf043f5cbf3e3f2c,0x3edbbf67bf62bef1,0xbf2c3f3ebf04bf5c,0x3f18bf4ebf46bf22,
0xbf4e3f183f71beac,0x3f3ebf2cbf22bf46,0xbf673edb3e163f7d,0x3f5cbf04bef1bf62,0xbf783e79bf80bd49,0x3f71beacbe95bf75,0xbf803d493e79bf78,0x3f7dbe16bdc9bf7f,
0xbf6f3eb8bf27bf42,0x3ee6bf65bf2cbf3e,0x3e893f773f133f51,0xbf58bf09bf4e3f18,0x3f7cbe2fbefcbf5f,0xbf1d3f4a3f043f5c,0xbd97bf7f3ecf3f6a,0x3f393f313f67bedb,
0xbf80bcc9bea1bf73,0x3f42bf27beacbf71,0xbdfb3f7e3e603f7a,0xbf13bf51bf783e79,0x3f7a3e60bdfbbf7e,0xbf5f3efc3e163f7d,0x3ea1bf733cc93f80,0x3ecf3f6a3f80bd49,
0x3cc93f803e893f77,0xbf1dbf4abf713eac,0xbf733ea1bf09bf58,0x3f13bf51bf18bf4e,0x3f09bf58bea13f73,0x3d973f7f3f783e79,0x3f773e893cc9bf80,0xbf6f3eb83d493f80,
0xbf6a3ecfbf4a3f1d,0x3efcbf5fbf2cbf3e,0xbf27bf423f13bf51,0x3f7a3e603f04bf5c,0x3f7c3e2fbf7f3d97,0xbf653ee63e163f7d,0x3dfb3f7e3f6fbeb8,0xbf31bf39bf673edb,
0x3f423f273f09bf58,0xbf7cbe2fbedb3f67,0x3f6fbeb8bf5f3efc,0xbf1d3f4a3f183f4e,0xbf773e89becfbf6a,0x3f31bf39bf04bf5c,0xbe603f7abd973f7f,0xbea1bf73bf803d49,
0xbf653ee63f133f51,0x3f09bf58bf2cbf3e,0xbcc93f80bdfbbf7e,0xbefcbf5fbf783e79,0x3dfbbf7e3f80bcc9,0x3ecf3f6a3f7dbe16,0xbf51bf13bf65bee6,0x3f7f3d973eacbf71,
0x3f773e89bf7abe60,0xbf7c3e2fbd493f80,0x3ecf3f6a3f65bee6,0xbf42bf27bf4e3f18,0xbee63f65becf3f6a,0x3cc9bf80bf78be79,0xbf7a3e60be89bf77,0x3f4abf1dbedbbf67,
0xbf7e3dfb3f7cbe2f,0x3f58bf09beacbf71,0xbf39bf31bf273f42,0x3f733ea13f04bf5c,0x3d97bf7f3cc9bf80,0x3eb83f6f3f7dbe16,0x3f51bf133f1d3f4a,0xbefc3f5f3f3e3f2c,
0x3f7a3e60be893f77,0xbf7e3dfbbd493f80,0x3f65bee63f6abecf,0xbf313f393f183f4e,0x3ecfbf6abf65bee6,0xbd973f7f3f783e79,0xbe89bf773e603f7a,0x3f133f513f67bedb,
0xbf7c3e2fbdfbbf7e,0x3f5fbefcbeacbf71,0xbf273f42bf313f39,0x3eb8bf6fbf5cbf04,0xbcc93f803f7f3d97,0xbea1bf73bf7d3e16,0x3f1d3f4abf13bf51,0xbf58bf09bf2c3f3e,
0x3f583f093f423f27,0xbf73bea1bedb3f67,0x3efc3f5fbf6f3eb8,0xbf31bf39bf4e3f18,0x3f6abecfbf773e89,0xbf4a3f1d3f043f5c,0x3f7f3d973e60bf7a,0xbf7c3e2f3d493f80,
0xbf513f13bf653ee6,0x3f27bf42bf2cbf3e,0xbf7e3dfb3cc9bf80,0x3f6fbeb8be79bf78,0x3cc93f803dfbbf7e,0xbe89bf77bf7d3e16,0xbee63f653f513f13,0x3e60bf7abf71beac,
0x3e893f773f80bcc9,0xbecfbf6abf713eac,0x3f093f58bea1bf73,0xbf27bf42bf4e3f18,0xbea13f73bf58bf09,0x3e2fbf7cbf78be79,0xbcc93f80be893f77,0xbdfbbf7ebf803d49,
0xbf4a3f1d3ecf3f6a,0x3f31bf39bf2cbf3e,0xbf133f513f42bf27,0x3ee6bf65bf5cbf04,0xbf7f3d973e2fbf7c,0x3f7abe60be16bf7d,0xbf6f3eb8bf7e3dfb,0x3f5fbefcbedbbf67,
0xbf423f273f6fbeb8,0x3f39bf31bf2cbf3e,0xbf513f133e893f77,0x3f4abf1dbf18bf4e,0xbf5f3efcbf7c3e2f,0x3f58bf09bf04bf5c,0xbf6a3ecfbd97bf7f,0x3f65bee6bedbbf67,
0xbf733ea13f803cc9,0x3f6fbeb8beacbf71,0xbf7a3e60bdfb3f7e,0x3f77be89be79bf78,0xbf7e3dfbbf7abe60,0x3f7cbe2fbe16bf7d,0xbf803cc93ea1bf73,0x3f7fbd97bd49bf80,
0x8000bf80bf800000,0xbf6dbec43f800000,0x8000bf80bf800000,0x3ec4bf6d3f800000,0x8000bf80bf800000,0x3f6d3ec43f800000,0x8000bf80bf800000,0xbec43f6d3f800000,
0x8000bf80bf800000,0xbf6dbec43f800000,0x8000bf80bf800000,0x3ec4bf6d3f800000,0x8000bf80bf800000,0x3f6d3ec43f800000,0x8000bf80bf800000,0xbec43f6d3f800000,
0x3e95bf75bf78be79,0x3f18bf4e3f713eac,0x3dc9bf7fbf80bd49,0xbf67bedb3f7d3e16,0x3f22bf46bf4ebf18,0xbf5c3f043f3e3f2c,0x3ef1bf62bf67bedb,0x3f2c3f3e3f5c3f04,
0x3f62bef1bf04bf5c,0x3f7dbe163edb3f67,0x3f46bf22bf2cbf3e,0xbeacbf713f183f4e,0x3f7fbdc9be16bf7d,0xbf78be793d493f80,0x3f75be95beacbf71,0xbd493f803e793f78,
0x3f55bf0ebf22bf46,0x3e953f753ef13f62,0x3f7bbe48be95bf75,0xbf7fbdc93dc93f7f,0x3e48bf7bbf7fbdc9,0xbf62bef13f753e95,0x3f0ebf55bf62bef1,0x3f46bf223f463f22,
0x3f0e3f553f46bf22,0xbf753e95bf623ef1,0x3e483f7b3f75be95,0x3dc9bf7fbf7f3dc9,0x3f7b3e483dc9bf7f,0x3ef1bf62be953f75,0x3f553f0e3ef1bf62,0x3f223f46bf223f46,
0x3f623ef13eacbf71,0xbf3ebf2cbf183f4e,0x3f7fbdc9be79bf78,0xbe163f7dbd493f80,0x3f46bf22bf3ebf2c,0x3f67bedb3f043f5c,0x3e95bf75bf7dbe16,0xbf5cbf043f673edb,
0xbf753e953edb3f67,0x3f80bd49be16bf7d,0xbf223f463f5c3f04,0xbf18bf4ebf2cbf3e,0xbdc93f7f3f80bd49,0xbeac3f71bf78be79,0x3ef13f623f4ebf18,0x3f78be79bf713eac,
0xbec43f6d3f7b3e48,0x3f553f0ebf55bf0e,0xbf6d3ec43f0e3f55,0xbf7b3e48be48bf7b,0xbf6dbec4be483f7b,0x3f0ebf553f0ebf55,0xbec4bf6dbf553f0e,0x3e483f7b3f7bbe48,
0x3ec4bf6dbf7bbe48,0xbf55bf0e3f553f0e,0x3f6dbec4bf0ebf55,0x3f7bbe483e483f7b,0x3f6d3ec43e48bf7b,0xbf0e3f55bf0e3f55,0x3ec43f6d3f55bf0e,0xbe48bf7bbf7b3e48,
0xbf46bf22bedb3f67,0xbf2cbf3e3f4ebf18,0xbf753e953f043f5c,0x3e163f7dbd49bf80,0x3f62bef1bf2cbf3e,0xbf713eac3e793f78,0x3dc9bf7fbf7d3e16,0x3f783e793f713eac,
0x3f7fbdc9beacbf71,0x3f803d49be163f7d,0x3ef1bf62bf78be79,0xbf4ebf183f3e3f2c,0xbe953f753f803d49,0x3edbbf67bf5cbf04,0x3f223f463f18bf4e,0xbf5c3f04bf673edb,
0x3f7bbe48bef1bf62,0x3dc93f7fbdc93f7f,0x3f0e3f553f22bf46,0xbef1bf62bf753e95,0xbf55bf0ebe953f75,0xbf223f463f46bf22,0x3e48bf7bbf7f3dc9,0x3e95bf753f623ef1,
0x3e483f7b3f62bef1,0xbf7f3dc9bf7fbdc9,0xbf553f0e3f463f22,0x3f62bef1be95bf75,0x3f0ebf55bf75be95,0xbf46bf223f223f46,0x3f7b3e48bdc9bf7f,0x3f753e95bef13f62,
0xbf463f223f5c3f04,0x3f4ebf18beacbf71,0x3ef13f623f2cbf3e,0xbf673edbbf7d3e16,0x3f75be95bf18bf4e,0x3f78be79bd493f80,0xbdc9bf7fbf673edb,0xbf803d493f783e79,
0xbf7fbdc93e793f78,0x3f7d3e163edbbf67,0xbe953f753f80bd49,0xbf71beacbf4ebf18,0x3f623ef13e16bf7d,0x3f5c3f04bf3e3f2c,0x3f22bf46bf71beac,0xbf3ebf2c3f043f5c,
0x3d49bf80bf80bcc9,0xbf6abecf3f7f3d97,0x3e16bf7dbf7ebdfb,0x3efcbf5f3f7c3e2f,0x3e79bf78bf7abe60,0x3f513f133f773e89,0x3eacbf71bf73bea1,0xbf273f423f6f3eb8,
0x3edbbf67bf6abecf,0xbf31bf393f653ee6,0x3f04bf5cbf5fbefc,0x3f4abf1d3f583f09,0x3f18bf4ebf51bf13,0x3f093f583f4a3f1d,0x3f2cbf3ebf42bf27,0xbf653ee63f393f31,
0x3edbbf67bf6fbeb8,0x3f31bf393f5f3efc,0x3e16bf7dbf7fbd97,0xbf65bee63f7a3e60,0x3f5cbf04bf13bf51,0xbf7a3e603ee63f65,0x3f2cbf3ebf4abf1d,0x3efc3f5f3f313f39,
0x3f803d49bcc9bf80,0x3f6f3eb8bdfb3f7e,0x3f78be79bea1bf73,0x3d97bf7f3e2f3f7c,0x3f4e3f183f09bf58,0xbf13bf51bf273f42,0x3f713eac3e89bf77,0xbf1d3f4abecf3f6a,
0x3f71beacbee6bf65,0x3d973f7f3e603f7a,0x3f7d3e163cc9bf80,0xbf6abecfbe893f77,0x3e79bf78bf7ebdfb,0xbf5fbefc3f6f3eb8,0x3f2cbf3ebf51bf13,0x3f58bf093f273f42,
0xbd493f803f7fbd97,0xbf73bea1bf7cbe2f,0xbf043f5c3f6a3ecf,0x3f39bf31bf4abf1d,0x3f4e3f183efcbf5f,0x3f4abf1dbf313f39,0x3edb3f673f58bf09,0x3e2f3f7cbf733ea1,
0x3f2c3f3e3f1dbf4a,0xbefcbf5fbf583f09,0x3f7d3e16bcc9bf80,0xbeb83f6fbea13f73,0x3f5cbf04bf27bf42,0x3f73bea13eb83f6f,0x3eacbf71bf7cbe2f,0xbf58bf093f5f3efc,
0xbf67bedbbe893f77,0x3f4a3f1d3f13bf51,0xbf783e793ecf3f6a,0xbcc9bf80bd97bf7f,0xbf183f4e3f653ee6,0xbf423f27bf31bf39,0x3d493f803f7abe60,0x3f7c3e2fbf7ebdfb,
0xbf3e3f2c3f513f13,0x3f093f58befcbf5f,0xbf7dbe163d973f7f,0xbf73bea13eb8bf6f,0xbf04bf5cbf393f31,0x3f6fbeb83f73bea1,0x3eacbf71bf7ebdfb,0xbefc3f5f3f583f09,
0x3edbbf67bf7abe60,0xbf51bf133f4a3f1d,0x3f78be79bee6bf65,0x3f7fbd973cc93f80,0x3f4e3f183ecfbf6a,0xbf393f31bf423f27,0x3d493f803f77be89,0x3dfbbf7ebf7cbe2f,
0xbeacbf71bf513f13,0xbe60bf7a3f7fbd97,0xbf7dbe163dfb3f7e,0xbe893f773ecfbf6a,0x3f783e79bcc9bf80,0xbf6fbeb8befc3f5f,0x3f2cbf3ebf65bee6,0x3f273f423f093f58,
0x3f803d49be60bf7a,0x3f7c3e2fbea13f73,0x3f04bf5cbf77be89,0xbf4abf1d3f313f39,0xbf183f4e3f6f3eb8,0x3f31bf39bf1dbf4a,0x3edb3f673f42bf27,0xbf733ea1bf7c3e2f,
0x3f673edb3dfbbf7e,0xbefc3f5fbf313f39,0xbe163f7d3f7cbe2f,0x3e60bf7abf65bee6,0xbf04bf5cbf273f42,0xbf653ee63f7abe60,0x3f2cbf3ebf6abecf,0x3f39bf313efc3f5f,
0xbd493f803f77be89,0xbf7ebdfbbf6fbeb8,0xbf783e793f093f58,0x3f7cbe2f3d97bf7f,0x3f18bf4ebf73bea1,0xbf42bf273f133f51,0x3f713eac3cc9bf80,0x3f6a3ecfbf1d3f4a,
0xbf80bd493ea13f73,0x3f7f3d973ecfbf6a,0xbe163f7d3f7abe60,0xbf7cbe2fbf5fbefc,0x3f783e79bdfbbf7e,0x3f773e89bf133f51,0x3eacbf71bf803cc9,0xbf6fbeb83f423f27,
0xbf67bedbbd973f7f,0x3f653ee63f39bf31,0xbf043f5c3f7c3e2f,0xbf58bf09bf1dbf4a,0x3f4e3f183e89bf77,0x3f4a3f1dbf583f09,0x3f2cbf3ebf6fbeb8,0xbf39bf313ee63f65,
0x3ec43f6d3f35bf35,0x3f800000bf35bf35,0xbf6d3ec43f353f35,0xbf8000003f353f35,0xbec4bf6dbf353f35,0x3f800000bf35bf35,0x3f6dbec4bf35bf35,0xbf8000003f353f35,
0x3ec43f6d3f35bf35,0x3f800000bf35bf35,0xbf6d3ec43f353f35,0xbf8000003f353f35,0xbec4bf6dbf353f35,0x3f800000bf35bf35,0x3f6dbec4bf35bf35,0xbf8000003f353f35,
0xbf803d493ef13f62,0xbf75be953f043f5c,0x3e793f783f46bf22,0x3f7f3dc9bf2cbf3e,0x3f713eacbdc9bf7f,0xbf46bf223e163f7d,0x3e16bf7dbf753e95,0x3f623ef1beacbf71,
0xbf3ebf2cbe953f75,0xbef1bf62be793f78,0xbf043f5c3f7f3dc9,0x3f223f463d49bf80,0x3edb3f673f22bf46,0xbdc9bf7fbf183f4e,0x3f4ebf18bf62bef1,0x3e953f753edbbf67,
0x3f22bf46bf7bbe48,0x3f0e3f553dc9bf7f,0x3ef13f623f0ebf55,0xbe48bf7bbef13f62,0x3dc93f7f3f55bf0e,0x3f7b3e48bf22bf46,0xbf75be953e483f7b,0xbf55bf0e3e953f75,
0x3f463f223e48bf7b,0xbf553f0e3f7f3dc9,0xbf623ef13f553f0e,0x3f7bbe48bf62bef1,0xbf7f3dc93f0e3f55,0xbe483f7b3f46bf22,0x3e95bf75bf7b3e48,0x3f0ebf55bf753e95,
0xbe793f783f75be95,0x3ef1bf62bf673edb,0x3f71beacbf46bf22,0x3dc93f7f3f04bf5c,0xbf4ebf18bdc93f7f,0xbf22bf463d493f80,0xbd493f803f62bef1,0x3f753e95bf18bf4e,
0xbf04bf5cbef13f62,0x3e953f753eacbf71,0xbedb3f673f7fbdc9,0xbf46bf223e793f78,0x3f7dbe16bf22bf46,0x3f7f3dc9bf3ebf2c,0xbf2cbf3ebe953f75,0xbf623ef13f7d3e16,
0x3e48bf7bbf6d3ec4,0xbf6dbec43f0e3f55,0x3f0e3f553ec4bf6d,0x3ec43f6d3e48bf7b,0xbf7bbe483ec43f6d,0x3ec4bf6dbf553f0e,0x3f55bf0ebf6dbec4,0xbf6d3ec43f7b3e48,
0xbe483f7b3f6dbec4,0x3f6d3ec4bf0ebf55,0xbf0ebf55bec43f6d,0xbec4bf6dbe483f7b,0x3f7b3e48bec4bf6d,0xbec43f6d3f55bf0e,0xbf553f0e3f6d3ec4,0x3f6dbec4bf7bbe48,
0xbf043f5c3f7fbdc9,0xbf223f463f71beac,0x3f67bedbbf62bef1,0xbe95bf75be793f78,0x3f183f4e3e95bf75,0xbef1bf62bd493f80,0xbd49bf80bf463f22,0x3f7f3dc9bf4ebf18,
0xbe79bf78bf223f46,0xbdc9bf7fbedb3f67,0xbeac3f713f75be95,0x3f623ef1bf04bf5c,0xbf7dbe163ef13f62,0x3f753e95bf2cbf3e,0x3f3e3f2c3dc9bf7f,0xbf463f223f7dbe16,
0x3f75be95bf55bf0e,0x3e483f7b3e95bf75,0xbf463f223f7b3e48,0x3f55bf0ebf7f3dc9,0x3f623ef1be48bf7b,0x3f0ebf55bf623ef1,0xbf7fbdc93f0e3f55,0xbf7bbe483f463f22,
0x3e953f753f0ebf55,0xbf7b3e483f753e95,0xbf22bf46be483f7b,0x3f0e3f55bdc9bf7f,0xbef13f623f7bbe48,0x3f553f0ebef1bf62,0x3dc9bf7fbf553f0e,0x3e48bf7bbf223f46,
0xbf2cbf3ebdc93f7f,0x3f223f46be79bf78,0x3f043f5c3e95bf75,0xbf623ef13f80bd49,0xbeacbf71bef13f62,0xbe95bf75be163f7d,0x3e163f7d3f22bf46,0x3f7fbdc9bf71beac,
0x3d49bf80bf463f22,0xbdc93f7f3f04bf5c,0xbe793f783f62bef1,0xbf75be953f3e3f2c,0x3edbbf67bf753e95,0x3ef1bf62bf4e3f18,0xbf183f4e3f7fbdc9,0x3f463f22bedbbf67,
0x3ea13f733f3ebf2c,0x3f803d49bf31bf39,0xbf7a3e603f183f4e,0xbf7dbe163f1d3f4a,0xbdfbbf7ebf5c3f04,0x3f783e79bf09bf58,0x3f80bcc9bedbbf67,0xbf71beac3ee63f65,
0xbd973f7f3f71beac,0x3f673edbbeb8bf6f,0xbf7cbe2f3e793f78,0xbf5cbf043e893f77,0x3e89bf77bf7d3e16,0x3f4e3f18be2fbf7c,0x3f6f3eb8bd49bf80,0xbf3ebf2c3d973f7f,
0xbf7ebdfb3eac3f71,0xbf67bedb3ecf3f6a,0x3e2f3f7c3f4ebf18,0x3f7d3e16bf27bf42,0x3f423f273e79bf78,0xbf04bf5cbe2f3f7c,0x3ecfbf6abf803d49,0x3f3e3f2cbdfbbf7e,
0xbe89bf77bf3e3f2c,0x3d49bf80bf313f39,0xbf583f093f5c3f04,0x3e793f783ee6bf65,0xbea13f733f7dbe16,0x3f18bf4ebf7a3e60,0x3f803cc9bedbbf67,0xbeac3f713f5fbefc,
0x3f51bf13bf67bedb,0x3eac3f713ea1bf73,0x3dfb3f7e3f4ebf18,0x3e16bf7dbf393f31,0x3cc93f803f5cbf04,0x3f783e79bf1dbf4a,0xbf65bee63d493f80,0xbf3ebf2c3e2f3f7c,
0x3e603f7a3f3ebf2c,0xbf80bd493f423f27,0xbf77be893e793f78,0x3f5c3f04beb8bf6f,0xbf6fbeb83e163f7d,0xbf183f4e3f77be89,0x3f42bf27bf71beac,0x3f67bedbbf7abe60,
0xbf133f513f803d49,0x3f3ebf2cbf7e3dfb,0x3f7fbd97bf18bf4e,0xbe163f7d3f31bf39,0xbf31bf39be793f78,0xbf04bf5cbd973f7f,0xbdfb3f7e3f67bedb,0x3f713eacbf13bf51,
0x3e60bf7abf713eac,0xbedb3f673f5fbefc,0xbf653ee63f5c3f04,0xbe79bf78beb83f6f,0x3f6a3ecfbe16bf7d,0x3f4e3f18bea1bf73,0xbe89bf77bf2c3f3e,0xbf803d493f583f09,
0x3f1dbf4abf80bd49,0xbf2cbf3e3e2f3f7c,0x3cc93f803f4ebf18,0xbe163f7d3f27bf42,0xbf27bf42be793f78,0x3f5cbf04bf80bcc9,0x3f7c3e2fbedbbf67,0xbf71beac3f1d3f4a,
0xbe893f773f71beac,0x3f673edbbf09bf58,0xbecfbf6abf043f5c,0xbe79bf78bea13f73,0x3f653ee6be16bf7d,0xbf183f4e3f6fbeb8,0xbf7a3e603f3e3f2c,0x3f80bd49bf5fbefc,
0xbf653ee63f673edb,0xbf713eac3f7c3e2f,0x3f803cc9bf18bf4e,0x3e16bf7dbf1d3f4a,0xbdfb3f7e3f5cbf04,0x3e79bf78bf313f39,0x3f13bf51bf803d49,0x3f3e3f2cbea1bf73,
0xbd97bf7fbf3e3f2c,0x3d49bf80bf093f58,0xbecf3f6a3f78be79,0x3f5c3f04befcbf5f,0xbf5fbefc3e163f7d,0x3f4e3f18becfbf6a,0x3f093f583eacbf71,0xbf673edb3f7f3d97,
0x3f6f3eb8beacbf71,0xbedb3f673f4abf1d,0xbf7fbd973f183f4e,0x3f7d3e16bf51bf13,0x3f133f513e79bf78,0x3f5cbf04bf7f3d97,0xbf4abf1d3d493f80,0xbf3ebf2c3eb83f6f,
0x3cc93f803f3ebf2c,0xbf80bd493f5f3efc,0xbea1bf73bf043f5c,0x3e793f783e60bf7a,0xbf093f583f7dbe16,0x3f4e3f18bee6bf65,0x3e89bf77bf673edb,0x3eacbf71bf393f31,
0x3cc9bf80bf3e3f2c,0xbd493f803ee6bf65,0xbdfb3f7e3f4ebf18,0xbf7dbe163f583f09,0x3e60bf7abf5c3f04,0x3e79bf78bf1d3f4a,0xbea13f733f67bedb,0x3f713eacbf39bf31,
0x3ecfbf6abf713eac,0xbedb3f673f42bf27,0xbefc3f5f3f78be79,0xbf5cbf043f133f51,0x3f13bf51bf7d3e16,0x3f18bf4ebf5f3efc,0xbf273f423f80bd49,0x3f3e3f2cbecfbf6a,
0xbec4bf6dbf353f35,0xbf6dbec43f353f35,0xbf6d3ec43f35bf35,0xbec43f6d3f35bf35,0x3ec43f6dbf353f35,0x3f6d3ec4bf35bf35,0x3f6dbec43f35bf35,0x3ec4bf6dbf353f35,
0xbec4bf6dbf353f35,0xbf6dbec43f353f35,0xbf6d3ec43f35bf35,0xbec43f6d3f35bf35,0x3ec43f6dbf353f35,0x3f6d3ec4bf35bf35,0x3f6dbec43f35bf35,0x3ec4bf6dbf353f35,
0xbf7d3e163f67bedb,0xbf2c3f3e3f62bef1,0xbeacbf71bf4e3f18,0xbf5cbf043f223f46,0x3f783e793f80bd49,0x3f67bedbbf7f3dc9,0xbd493f80bf783e79,0x3f183f4ebe95bf75,
0xbf4ebf183f713eac,0xbf803d493f753e95,0x3edbbf67bf7dbe16,0xbe79bf78bdc93f7f,0x3f043f5c3f3e3f2c,0x3f713eacbf46bf22,0xbf3e3f2cbf5cbf04,0xbe163f7d3ef1bf62,
0xbef13f62bf75be95,0x3dc93f7f3e48bf7b,0x3f223f463f463f22,0x3f753e95bf55bf0e,0xbe95bf75bf623ef1,0xbf46bf223f0e3f55,0xbf7fbdc93f7fbdc9,0xbf623ef13f7bbe48,
0xbf62bef13e95bf75,0xbf7f3dc93f7b3e48,0xbf463f22bf223f46,0xbe953f753f0ebf55,0x3f75be95bef1bf62,0x3f22bf46bf553f0e,0x3dc9bf7f3dc93f7f,0xbef1bf623e483f7b,
0x3d493f803e163f7d,0x3f043f5cbe95bf75,0xbf4e3f18bf2cbf3e,0xbedb3f673f22bf46,0xbf71beac3f783e79,0xbf7d3e163f7f3dc9,0xbe79bf78bf713eac,0xbf2cbf3e3ef13f62,
0xbf3ebf2cbf4ebf18,0xbf78be793f623ef1,0x3e16bf7d3f803d49,0xbeacbf713dc93f7f,0x3f67bedbbf5c3f04,0x3f18bf4ebf463f22,0x3f5c3f043edbbf67,0x3f803d49bf75be95,
0x3e483f7b3f7bbe48,0x3f0e3f55bec4bf6d,0x3f553f0ebf55bf0e,0x3f7b3e48bf6dbec4,0x3f7bbe483e483f7b,0x3f55bf0ebf6d3ec4,0x3f0ebf553f0ebf55,0x3e48bf7bbec43f6d,
0xbe48bf7bbf7b3e48,0xbf0ebf553ec43f6d,0xbf55bf0e3f553f0e,0xbf7bbe483f6d3ec4,0xbf7b3e48be48bf7b,0xbf553f0e3f6dbec4,0xbf0e3f55bf0e3f55,0xbe483f7b3ec4bf6d,
0xbd493f803e16bf7d,0x3e793f78bdc9bf7f,0xbf183f4e3f3e3f2c,0xbeac3f713ef1bf62,0x3f673edb3f5c3f04,0x3f7d3e16bf75be95,0x3f043f5cbf673edb,0x3f3e3f2cbf22bf46,
0xbf2cbf3e3f183f4e,0xbf5cbf043f463f22,0xbe16bf7dbf803d49,0xbedbbf673e953f75,0xbf713eacbf783e79,0xbf4e3f183f62bef1,0xbf78be793eacbf71,0xbf803d493f7f3dc9,
0xbf223f46bf22bf46,0xbef13f623f0ebf55,0xbe953f75bef13f62,0xbdc93f7f3e48bf7b,0xbf7f3dc9bdc93f7f,0xbf753e953f7bbe48,0xbf623ef13f75be95,0xbf463f223f55bf0e,
0xbf46bf223f46bf22,0xbf62bef13f553f0e,0xbf75be95bf62bef1,0xbf7fbdc93f7b3e48,0xbdc9bf7fbf7fbdc9,0xbe95bf753e483f7b,0xbef1bf623e953f75,0xbf22bf463f0e3f55,
0xbf7dbe16bf67bedb,0xbf80bd493f7f3dc9,0xbf71beac3f18bf4e,0xbf78be793f753e95,0xbf5cbf043f2c3f3e,0xbf67bedb3f623ef1,0xbf3ebf2cbf5c3f04,0xbf4ebf183f463f22,
0xbf18bf4ebeacbf71,0xbf2cbf3e3f223f46,0xbedbbf673f7dbe16,0xbf04bf5c3ef13f62,0xbe79bf78bd493f80,0xbeacbf713e953f75,0xbd49bf80bf78be79,0xbe16bf7d3dc93f7f,
0xbeb8bf6fbf423f27,0xbf65bee63f2c3f3e,0xbf773e893f51bf13,0xbf093f583f4ebf18,0x3e2f3f7cbf5f3efc,0x3f4a3f1dbf04bf5c,0x3f7fbd973f6abecf,0x3f31bf39bf673edb,
0x3cc9bf80bf733ea1,0xbf27bf423eac3f71,0xbf7ebdfb3f7abe60,0xbf513f133f78be79,0xbe603f7abf7e3dfb,0x3efc3f5fbe16bf7d,0x3f733ea13f80bcc9,0x3f6abecfbf803d49,
0xbf803cc93f77be89,0xbf4a3f1d3f71beac,0xbea1bf73bf583f09,0xbf51bf133f183f4e,0x3f583f093f733ea1,0x3f7fbd97bf78be79,0xbe893f77bf80bcc9,0x3eb83f6fbd49bf80,
0xbecfbf6a3f1d3f4a,0xbf5fbefc3f2c3f3e,0x3f42bf27bf51bf13,0x3e60bf7abf043f5c,0xbe2f3f7c3d973f7f,0x3ee63f65be16bf7d,0xbf7e3dfbbeb8bf6f,0xbf393f313f67bedb,
0xbf273f42bf58bf09,0xbe2f3f7c3edbbf67,0x3eb83f6f3efc3f5f,0x3f4a3f1dbf18bf4e,0xbe89bf77bf6a3ecf,0xbf39bf313f043f5c,0xbf7abe603f7f3d97,0xbf733ea13f80bd49,
0xbee6bf653f51bf13,0xbf58bf093f2c3f3e,0xbf80bcc9bf7e3dfb,0xbf5f3efc3f78be79,0x3f7e3dfbbcc9bf80,0x3f6abecfbf7d3e16,0x3f13bf51bee63f65,0x3d97bf7fbeac3f71,
0xbe893f77be603f7a,0x3e2f3f7c3d49bf80,0xbf6a3ecfbee6bf65,0xbf273f423f4ebf18,0xbf65bee63f6a3ecf,0xbf80bcc93f783e79,0xbe60bf7abf773e89,0xbf1dbf4a3edb3f67,
0xbdfbbf7ebe2fbf7c,0xbf09bf583eac3f71,0x3f31bf393f423f27,0x3ea1bf73bf043f5c,0x3f7f3d97bf80bcc9,0x3f6fbeb8bf7d3e16,0x3f133f513f4abf1d,0x3f5f3efcbf3ebf2c,
0xbe603f7a3f773e89,0x3dfb3f7e3d49bf80,0x3ee63f65becfbf6a,0x3f393f31bf18bf4e,0x3f6a3ecfbee63f65,0x3f7f3d97bf78be79,0x3f77be893f7abe60,0x3f51bf13bf673edb,
0xbe2fbf7cbf7e3dfb,0xbefcbf5f3eac3f71,0xbf42bf273f393f31,0xbf6fbeb83f5c3f04,0xbf80bcc93d97bf7f,0xbf733ea13f7dbe16,0xbf4a3f1dbf513f13,0xbf093f583f2cbf3e,
0xbf093f583f27bf42,0xbea13f733edbbf67,0xbf5f3efc3eb83f6f,0xbf393f313f4ebf18,0x3ecf3f6a3e893f77,0x3f1d3f4abf04bf5c,0xbd973f7fbf7abe60,0x3e2f3f7cbd49bf80,
0xbf13bf513ee63f65,0xbf42bf273f2c3f3e,0xbdfbbf7ebf80bcc9,0xbeb8bf6f3e793f78,0xbf803cc9bf7ebdfb,0xbf773e893f7dbe16,0xbf65bee63f13bf51,0xbf7abe603f713eac,
0xbf773e89bcc9bf80,0xbf6a3ecf3f71beac,0xbf583f09bf733ea1,0xbf423f273f4ebf18,0xbf73bea1bf093f58,0xbf7cbe2f3f783e79,0xbf80bcc93f773e89,0xbf7e3dfb3f80bd49,
0xbf1dbf4a3f6abecf,0xbf39bf313f2c3f3e,0xbf51bf13bf27bf42,0xbf65bee63f5c3f04,0xbd97bf7fbf7cbe2f,0xbe60bf7a3e163f7d,0xbeb8bf6f3dfb3f7e,0xbefcbf5f3edb3f67,
0xbf27bf42beb8bf6f,0xbf31bf393f2c3f3e,0xbf13bf513f77be89,0xbf1dbf4a3f183f4e,0xbefcbf5f3e2f3f7c,0xbf09bf583f043f5c,0xbecfbf6abf7f3d97,0xbee6bf653edb3f67,
0xbea1bf733cc9bf80,0xbeb8bf6f3eac3f71,0xbe60bf7a3f7e3dfb,0xbe89bf773e793f78,0xbdfbbf7ebe603f7a,0xbe2fbf7c3e163f7d,0xbcc9bf80bf73bea1,0xbd97bf7f3d493f80,
0x80003f803f003f00,0x80003f8080003f80,0x80003f8080003f80,0x80003f8080003f80,0x80003f8080003f80,0x80003f8080003f80,0x80003f8080003f80,0x80003f8080003f80,
0x80003f8080003f80,0x80003f8080003f80,0x80003f8080003f80,0x80003f8080003f80,0x80003f8080003f80,0x80003f8080003f80,0x80003f8080003f80,0x80003f8080003f80,
0x3e48bf7bbe483f7b,0x3e48bf7bbe483f7b,0x8000bf803f003f00,0x3f800000bf800000,0x3f0ebf55bf0e3f55,0x3f0ebf55bf0e3f55,0x3ec4bf6dbec43f6d,0x3ec4bf6dbec43f6d,
0x3f55bf0ebf553f0e,0x3f55bf0ebf553f0e,0x3f35bf35bf353f35,0x3f35bf35bf353f35,0x3f7bbe48bf7b3e48,0x3f7bbe48bf7b3e48,0x3f6dbec4bf6d3ec4,0x3f6dbec4bf6d3ec4,
0xbf353f35bf353f35,0xbf353f35bf353f35,0xbf6d3ec4bf6d3ec4,0xbf6d3ec4bf6d3ec4,0x80003f803f003f00,0x8000bf808000bf80,0xbec43f6dbec43f6d,0xbec43f6dbec43f6d,
0xbf35bf35bf35bf35,0xbf35bf35bf35bf35,0xbec4bf6dbec4bf6d,0xbec4bf6dbec4bf6d,0xbf800000bf800000,0xbf800000bf800000,0xbf6dbec4bf6dbec4,0xbf6dbec4bf6dbec4,
0x3f7b3e48bf7bbe48,0x3f7b3e48bf7bbe48,0x3f6dbec4bf6d3ec4,0x3f6dbec4bf6d3ec4,0x3f0ebf55bf0e3f55,0x3f0ebf55bf0e3f55,0x8000bf803f003f00,0xbf8000003f800000,
0xbf553f0e3f55bf0e,0xbf553f0e3f55bf0e,0xbec43f6d3ec4bf6d,0xbec43f6d3ec4bf6d,0x3e483f7bbe48bf7b,0x3e483f7bbe48bf7b,0x3f353f35bf35bf35,0x3f353f35bf35bf35,
0x8000bf808000bf80,0x8000bf808000bf80,0x3f35bf353f35bf35,0x3f35bf353f35bf35,0x3f8000003f800000,0x3f8000003f800000,0x3f353f353f353f35,0x3f353f353f353f35,
0x80003f803f003f00,0x80003f8080003f80,0xbf353f35bf353f35,0xbf353f35bf353f35,0xbf800000bf800000,0xbf800000bf800000,0xbf35bf35bf35bf35,0xbf35bf35bf35bf35,
0xbf7bbe483f7b3e48,0xbf7bbe483f7b3e48,0xbf353f353f35bf35,0xbf353f353f35bf35,0x3f0ebf55bf0e3f55,0x3f0ebf55bf0e3f55,0xbec4bf6d3ec43f6d,0xbec4bf6d3ec43f6d,
0x3f55bf0ebf553f0e,0x3f55bf0ebf553f0e,0x8000bf803f003f00,0x3f800000bf800000,0x3e483f7bbe48bf7b,0x3e483f7bbe48bf7b,0x3f6d3ec4bf6dbec4,0x3f6d3ec4bf6dbec4,
0xbf353f35bf353f35,0xbf353f35bf353f35,0xbf6dbec4bf6dbec4,0xbf6dbec4bf6dbec4,0x3f8000003f800000,0x3f8000003f800000,0x3ec43f6d3ec43f6d,0x3ec43f6d3ec43f6d,
0xbf35bf35bf35bf35,0xbf35bf35bf35bf35,0x3ec4bf6d3ec4bf6d,0x3ec4bf6d3ec4bf6d,0x80003f803f003f00,0x8000bf808000bf80,0xbf6d3ec4bf6d3ec4,0xbf6d3ec4bf6d3ec4,
0xbe483f7b3e48bf7b,0xbe483f7b3e48bf7b,0x3f6d3ec4bf6dbec4,0x3f6d3ec4bf6dbec4,0x3f0ebf55bf0e3f55,0x3f0ebf55bf0e3f55,0xbf35bf353f353f35,0xbf35bf353f353f35,
0xbf553f0e3f55bf0e,0xbf553f0e3f55bf0e,0x3ec43f6dbec4bf6d,0x3ec43f6dbec4bf6d,0x3f7bbe48bf7b3e48,0x3f7bbe48bf7b3e48,0x8000bf803f003f00,0xbf8000003f800000,
0xbf800000bf003f00,0xbf35bf35bf353f35,0xbf7fbdc9bdc93f7f,0x3f7f3dc93dc9bf7f,0xbf7bbe48be483f7b,0x3f7b3e483e48bf7b,0xbf75be95be953f75,0x3f753e953e95bf75,
0xbf6dbec4bec43f6d,0x3f6d3ec43ec4bf6d,0xbf62bef1bef13f62,0x3f623ef13ef1bf62,0xbf55bf0ebf0e3f55,0x3f553f0e3f0ebf55,0xbf46bf22bf223f46,0x3f463f223f22bf46,
0x3f753e95be953f75,0xbf75be953e95bf75,0x3f800000bf003f00,0xbf353f35bf35bf35,0x3f223f46bf463f22,0xbf22bf463f46bf22,0x3f553f0ebf0e3f55,0xbf55bf0e3f0ebf55,
0x3dc93f7fbf7f3dc9,0xbdc9bf7f3f7fbdc9,0x3ec43f6dbf6d3ec4,0xbec4bf6d3f6dbec4,0xbef13f62bf62bef1,0x3ef1bf623f623ef1,0xbe483f7bbf7bbe48,0x3e48bf7b3f7b3e48,
0xbf0ebf55bf553f0e,0x3f0e3f553f55bf0e,0xbdc9bf7fbf7f3dc9,0x3dc93f7f3f7fbdc9,0xbf800000bf003f00,0x3f353f353f35bf35,0xbf62bef1bef13f62,0x3f623ef13ef1bf62,
0x3f7bbe48be48bf7b,0xbf7b3e483e483f7b,0x3f753e953e95bf75,0xbf75be95be953f75,0x3ec4bf6dbf6dbec4,0xbec43f6d3f6d3ec4,0x3f46bf22bf22bf46,0xbf463f223f223f46,
0xbef13f62bf62bef1,0x3ef1bf623f623ef1,0x3e483f7bbf7b3e48,0xbe48bf7b3f7bbe48,0x3f463f22bf223f46,0xbf46bf223f22bf46,0x3f800000bf003f00,0x3f35bf353f353f35,
0x3dc9bf7f3f7f3dc9,0xbdc93f7fbf7fbdc9,0xbf0ebf553f55bf0e,0x3f0e3f55bf553f0e,0xbf75be953e95bf75,0x3f753e95be953f75,0xbf6d3ec4bec4bf6d,0x3f6dbec43ec43f6d,
0x3f6d3ec43ec4bf6d,0xbf6dbec4bec43f6d,0x3e953f753f75be95,0xbe95bf75bf753e95,0xbf0e3f553f553f0e,0x3f0ebf55bf55bf0e,0xbf7f3dc93dc93f7f,0x3f7fbdc9bdc9bf7f,
0xbf800000bf003f00,0xbf35bf35bf353f35,0xbf22bf46bf463f22,0x3f223f463f46bf22,0x3e48bf7bbf7bbe48,0xbe483f7b3f7b3e48,0x3f62bef1bef1bf62,0xbf623ef13ef13f62,
0x3f22bf463f463f22,0xbf223f46bf46bf22,0xbec4bf6d3f6dbec4,0x3ec43f6dbf6d3ec4,0x3e953f75bf753e95,0xbe95bf753f75be95,0x3f7b3e48be483f7b,0xbf7bbe483e48bf7b,
0x3ef13f62bf623ef1,0xbef1bf623f62bef1,0x3f800000bf003f00,0xbf353f35bf35bf35,0xbf7fbdc93dc9bf7f,0x3f7f3dc9bdc93f7f,0xbf0e3f55bf55bf0e,0x3f0ebf553f553f0e,
0xbe48bf7bbf7b3e48,0x3e483f7b3f7bbe48,0x3f62bef1bef1bf62,0xbf623ef13ef13f62,0xbec43f6d3f6d3ec4,0x3ec4bf6dbf6dbec4,0xbf7fbdc9bdc93f7f,0x3f7f3dc93dc9bf7f,
0x3f55bf0ebf0ebf55,0xbf553f0e3f0e3f55,0x3f463f223f22bf46,0xbf46bf22bf223f46,0xbf800000bf003f00,0x3f353f353f35bf35,0xbe95bf75bf753e95,0x3e953f753f75be95,
0xbf22bf463f46bf22,0x3f223f46bf463f22,0xbf553f0ebf0ebf55,0x3f55bf0e3f0e3f55,0x3ef13f62bf623ef1,0xbef1bf623f62bef1,0x3f6dbec43ec43f6d,0xbf6d3ec4bec4bf6d,
0xbe95bf753f75be95,0x3e953f75bf753e95,0xbf7b3e48be48bf7b,0x3f7bbe483e483f7b,0x3dc93f7fbf7f3dc9,0xbdc9bf7f3f7fbdc9,0x3f800000bf003f00,0x3f35bf353f353f35,
0x80003f803f003f00,0x80003f8080003f80,0xbf800000bf800000,0xbf800000bf800000,0x8000bf808000bf80,0x8000bf808000bf80,0x3f8000003f800000,0x3f8000003f800000,
0x80003f8080003f80,0x80003f8080003f80,0xbf800000bf800000,0xbf800000bf800000,0x8000bf808000bf80,0x8000bf808000bf80,0x3f8000003f800000,0x3f8000003f800000,
0x3f7b3e48bf7bbe48,0x3f7b3e48bf7bbe48,0x8000bf803f003f00,0x3f800000bf800000,0xbf55bf0e3f553f0e,0xbf55bf0e3f553f0e,0xbec43f6d3ec4bf6d,0xbec43f6d3ec4bf6d,
0x3f0e3f55bf0ebf55,0x3f0e3f55bf0ebf55,0x3f35bf35bf353f35,0x3f35bf35bf353f35,0xbe48bf7b3e483f7b,0xbe48bf7b3e483f7b,0xbf6d3ec43f6dbec4,0xbf6d3ec43f6dbec4,
0x3f35bf353f35bf35,0x3f35bf353f35bf35,0x3ec43f6d3ec43f6d,0x3ec43f6d3ec43f6d,0x80003f803f003f00,0x8000bf808000bf80,0xbf6dbec4bf6dbec4,0xbf6dbec4bf6dbec4,
0x3f353f353f353f35,0x3f353f353f353f35,0xbf6d3ec4bf6d3ec4,0xbf6d3ec4bf6d3ec4,0xbf800000bf800000,0xbf800000bf800000,0x3ec4bf6d3ec4bf6d,0x3ec4bf6d3ec4bf6d,
0x3e48bf7bbe483f7b,0x3e48bf7bbe483f7b,0xbf6d3ec43f6dbec4,0xbf6d3ec43f6dbec4,0x3f553f0ebf55bf0e,0x3f553f0ebf55bf0e,0x8000bf803f003f00,0xbf8000003f800000,
0x3f0e3f55bf0ebf55,0x3f0e3f55bf0ebf55,0x3ec4bf6dbec43f6d,0x3ec4bf6dbec43f6d,0xbf7b3e483f7bbe48,0xbf7b3e483f7bbe48,0x3f353f35bf35bf35,0x3f353f35bf35bf35,
0x8000bf808000bf80,0x8000bf808000bf80,0x3f353f353f353f35,0x3f353f353f353f35,0xbf800000bf800000,0xbf800000bf800000,0x3f35bf353f35bf35,0x3f35bf353f35bf35,
0x80003f803f003f00,0x80003f8080003f80,0xbf35bf35bf35bf35,0xbf35bf35bf35bf35,0x3f8000003f800000,0x3f8000003f800000,0xbf353f35bf353f35,0xbf353f35bf353f35,
0x3e48bf7bbe483f7b,0x3e48bf7bbe483f7b,0xbf353f353f35bf35,0xbf353f353f35bf35,0xbf55bf0e3f553f0e,0xbf55bf0e3f553f0e,0x3ec43f6dbec4bf6d,0x3ec43f6dbec4bf6d,
0x3f0e3f55bf0ebf55,0x3f0e3f55bf0ebf55,0x8000bf803f003f00,0x3f800000bf800000,0x3f7bbe48bf7b3e48,0x3f7bbe48bf7b3e48,0xbf6dbec43f6d3ec4,0xbf6dbec43f6d3ec4,
0x3f35bf353f35bf35,0x3f35bf353f35bf35,0xbec43f6dbec43f6d,0xbec43f6dbec43f6d,0x3f8000003f800000,0x3f8000003f800000,0xbf6d3ec4bf6d3ec4,0xbf6d3ec4bf6d3ec4,
0x3f353f353f353f35,0x3f353f353f353f35,0xbf6dbec4bf6dbec4,0xbf6dbec4bf6dbec4,0x80003f803f003f00,0x8000bf808000bf80,0xbec4bf6dbec4bf6d,0xbec4bf6dbec4bf6d,
0x3f7b3e48bf7bbe48,0x3f7b3e48bf7bbe48,0xbf6dbec43f6d3ec4,0xbf6dbec43f6d3ec4,0x3f553f0ebf55bf0e,0x3f553f0ebf55bf0e,0xbf35bf353f353f35,0xbf35bf353f353f35,
0x3f0e3f55bf0ebf55,0x3f0e3f55bf0ebf55,0xbec4bf6d3ec43f6d,0xbec4bf6d3ec43f6d,0x3e483f7bbe48bf7b,0x3e483f7bbe48bf7b,0x8000bf803f003f00,0xbf8000003f800000,
0xbf800000bf003f00,0xbf35bf35bf353f35,0x3dc9bf7fbf7fbdc9,0xbdc93f7f3f7f3dc9,0x3f7b3e483e48bf7b,0xbf7bbe48be483f7b,0xbe953f753f753e95,0x3e95bf75bf75be95,
0xbf6dbec4bec43f6d,0x3f6d3ec43ec4bf6d,0x3ef1bf62bf62bef1,0xbef13f623f623ef1,0x3f553f0e3f0ebf55,0xbf55bf0ebf0e3f55,0xbf223f463f463f22,0x3f22bf46bf46bf22,
0xbe953f75bf75be95,0x3e95bf753f753e95,0x3f800000bf003f00,0xbf353f35bf35bf35,0x3f46bf223f223f46,0xbf463f22bf22bf46,0xbf55bf0e3f0ebf55,0x3f553f0ebf0e3f55,
0xbf7f3dc9bdc9bf7f,0x3f7fbdc93dc93f7f,0x3ec43f6dbf6d3ec4,0xbec4bf6d3f6dbec4,0x3f623ef1bef13f62,0xbf62bef13ef1bf62,0x3e48bf7b3f7b3e48,0xbe483f7bbf7bbe48,
0x3f0e3f553f55bf0e,0xbf0ebf55bf553f0e,0xbf7f3dc93dc93f7f,0x3f7fbdc9bdc9bf7f,0xbf800000bf003f00,0x3f353f353f35bf35,0x3ef1bf62bf62bef1,0xbef13f623f623ef1,
0xbf7b3e483e483f7b,0x3f7bbe48be48bf7b,0x3e95bf75bf75be95,0xbe953f753f753e95,0x3ec4bf6dbf6dbec4,0xbec43f6d3f6d3ec4,0x3f223f463f46bf22,0xbf22bf46bf463f22,
0x3f623ef1bef13f62,0xbf62bef13ef1bf62,0xbe48bf7b3f7bbe48,0x3e483f7bbf7b3e48,0xbf223f46bf46bf22,0x3f22bf463f463f22,0x3f800000bf003f00,0x3f35bf353f353f35,
0xbf7fbdc93dc9bf7f,0x3f7f3dc9bdc93f7f,0x3f0e3f55bf553f0e,0xbf0ebf553f55bf0e,0x3e95bf753f753e95,0xbe953f75bf75be95,0xbf6d3ec4bec4bf6d,0x3f6dbec43ec43f6d,
0x3f6d3ec43ec4bf6d,0xbf6dbec4bec43f6d,0xbf753e953e953f75,0x3f75be95be95bf75,0x3f0ebf55bf55bf0e,0xbf0e3f553f553f0e,0x3dc93f7f3f7fbdc9,0xbdc9bf7fbf7f3dc9,
0xbf800000bf003f00,0xbf35bf35bf353f35,0x3f46bf22bf22bf46,0xbf463f223f223f46,0xbe483f7b3f7b3e48,0x3e48bf7bbf7bbe48,0xbef1bf62bf623ef1,0x3ef13f623f62bef1,
0x3f463f22bf223f46,0xbf46bf223f22bf46,0xbec4bf6d3f6dbec4,0x3ec43f6dbf6d3ec4,0x3f75be953e953f75,0xbf753e95be95bf75,0xbf7bbe483e48bf7b,0x3f7b3e48be483f7b,
0xbf623ef1bef1bf62,0x3f62bef13ef13f62,0x3f800000bf003f00,0xbf353f35bf35bf35,0xbdc93f7fbf7fbdc9,0x3dc9bf7f3f7f3dc9,0x3f0ebf553f553f0e,0xbf0e3f55bf55bf0e,
0x3e483f7b3f7bbe48,0xbe48bf7bbf7b3e48,0xbef1bf62bf623ef1,0x3ef13f623f62bef1,0xbec43f6d3f6d3ec4,0x3ec4bf6dbf6dbec4,0x3dc9bf7fbf7fbdc9,0xbdc93f7f3f7f3dc9,
0xbf553f0e3f0e3f55,0x3f55bf0ebf0ebf55,0x3f22bf46bf46bf22,0xbf223f463f463f22,0xbf800000bf003f00,0x3f353f353f35bf35,0x3f75be95be95bf75,0xbf753e953e953f75,
0xbf463f22bf22bf46,0x3f46bf223f223f46,0x3f55bf0e3f0e3f55,0xbf553f0ebf0ebf55,0xbf623ef1bef1bf62,0x3f62bef13ef13f62,0x3f6dbec43ec43f6d,0xbf6d3ec4bec4bf6d,
0xbf753e95be95bf75,0x3f75be953e953f75,0x3f7bbe483e483f7b,0xbf7b3e48be48bf7b,0xbf7f3dc9bdc9bf7f,0x3f7fbdc93dc93f7f,0x3f800000bf003f00,0x3f35bf353f353f35,
0x80003f803f003f00,0x80003f8080003f80,0x8000bf808000bf80,0x8000bf808000bf80,0x80003f8080003f80,0x80003f8080003f80,0x8000bf808000bf80,0x8000bf808000bf80,
0x80003f8080003f80,0x80003f8080003f80,0x8000bf808000bf80,0x8000bf808000bf80,0x80003f8080003f80,0x80003f8080003f80,0x8000bf808000bf80,0x8000bf808000bf80,
0xbe483f7b3e48bf7b,0xbe483f7b3e48bf7b,0x8000bf803f003f00,0x3f800000bf800000,0xbf0e3f553f0ebf55,0xbf0e3f553f0ebf55,0x3ec4bf6dbec43f6d,0x3ec4bf6dbec43f6d,
0xbf553f0e3f55bf0e,0xbf553f0e3f55bf0e,0x3f35bf35bf353f35,0x3f35bf35bf353f35,0xbf7b3e483f7bbe48,0xbf7b3e483f7bbe48,0x3f6dbec4bf6d3ec4,0x3f6dbec4bf6d3ec4,
0xbf353f35bf353f35,0xbf353f35bf353f35,0x3f6dbec43f6dbec4,0x3f6dbec43f6dbec4,0x80003f803f003f00,0x8000bf808000bf80,0x3ec4bf6d3ec4bf6d,0x3ec4bf6d3ec4bf6d,
0xbf35bf35bf35bf35,0xbf35bf35bf35bf35,0x3ec43f6d3ec43f6d,0x3ec43f6d3ec43f6d,0xbf800000bf800000,0xbf800000bf800000,0x3f6d3ec43f6d3ec4,0x3f6d3ec43f6d3ec4,
0xbf7bbe483f7b3e48,0xbf7bbe483f7b3e48,0x3f6dbec4bf6d3ec4,0x3f6dbec4bf6d3ec4,0xbf0e3f553f0ebf55,0xbf0e3f553f0ebf55,0x8000bf803f003f00,0xbf8000003f800000,
0x3f55bf0ebf553f0e,0x3f55bf0ebf553f0e,0xbec43f6d3ec4bf6d,0xbec43f6d3ec4bf6d,0xbe48bf7b3e483f7b,0xbe48bf7b3e483f7b,0x3f353f35bf35bf35,0x3f353f35bf35bf35,
0x8000bf808000bf80,0x8000bf808000bf80,0xbf353f35bf353f35,0xbf353f35bf353f35,0x3f8000003f800000,0x3f8000003f800000,0xbf35bf35bf35bf35,0xbf35bf35bf35bf35,
0x80003f803f003f00,0x80003f8080003f80,0x3f35bf353f35bf35,0x3f35bf353f35bf35,0xbf800000bf800000,0xbf800000bf800000,0x3f353f353f353f35,0x3f353f353f353f35,
0x3f7b3e48bf7bbe48,0x3f7b3e48bf7bbe48,0xbf353f353f35bf35,0xbf353f353f35bf35,0xbf0e3f553f0ebf55,0xbf0e3f553f0ebf55,0xbec4bf6d3ec43f6d,0xbec4bf6d3ec43f6d,
0xbf553f0e3f55bf0e,0xbf553f0e3f55bf0e,0x8000bf803f003f00,0x3f800000bf800000,0xbe48bf7b3e483f7b,0xbe48bf7b3e483f7b,0x3f6d3ec4bf6dbec4,0x3f6d3ec4bf6dbec4,
0xbf353f35bf353f35,0xbf353f35bf353f35,0x3f6d3ec43f6d3ec4,0x3f6d3ec43f6d3ec4,0x3f8000003f800000,0x3f8000003f800000,0xbec4bf6dbec4bf6d,0xbec4bf6dbec4bf6d,
0xbf35bf35bf35bf35,0xbf35bf35bf35bf35,0xbec43f6dbec43f6d,0xbec43f6dbec43f6d,0x80003f803f003f00,0x8000bf808000bf80,0x3f6dbec43f6dbec4,0x3f6dbec43f6dbec4,
0x3e48bf7bbe483f7b,0x3e48bf7bbe483f7b,0x3f6d3ec4bf6dbec4,0x3f6d3ec4bf6dbec4,0xbf0e3f553f0ebf55,0xbf0e3f553f0ebf55,0xbf35bf353f353f35,0xbf35bf353f353f35,
0x3f55bf0ebf553f0e,0x3f55bf0ebf553f0e,0x3ec43f6dbec4bf6d,0x3ec43f6dbec4bf6d,0xbf7b3e483f7bbe48,0xbf7b3e483f7bbe48,0x8000bf803f003f00,0xbf8000003f800000,
0xbf800000bf003f00,0xbf35bf35bf353f35,0x3f7f3dc93dc9bf7f,0xbf7fbdc9bdc93f7f,0xbf7bbe48be483f7b,0x3f7b3e483e48bf7b,0x3f753e953e95bf75,0xbf75be95be953f75,
0xbf6dbec4bec43f6d,0x3f6d3ec43ec4bf6d,0x3f623ef13ef1bf62,0xbf62bef1bef13f62,0xbf55bf0ebf0e3f55,0x3f553f0e3f0ebf55,0x3f463f223f22bf46,0xbf46bf22bf223f46,
0xbf75be953e95bf75,0x3f753e95be953f75,0x3f800000bf003f00,0xbf353f35bf35bf35,0xbf22bf463f46bf22,0x3f223f46bf463f22,0x3f553f0ebf0e3f55,0xbf55bf0e3f0ebf55,
0xbdc9bf7f3f7fbdc9,0x3dc93f7fbf7f3dc9,0x3ec43f6dbf6d3ec4,0xbec4bf6d3f6dbec4,0x3ef1bf623f623ef1,0xbef13f62bf62bef1,0xbe483f7bbf7bbe48,0x3e48bf7b3f7b3e48,
0xbf0ebf55bf553f0e,0x3f0e3f553f55bf0e,0x3dc93f7f3f7fbdc9,0xbdc9bf7fbf7f3dc9,0xbf800000bf003f00,0x3f353f353f35bf35,0x3f623ef13ef1bf62,0xbf62bef1bef13f62,
0x3f7bbe48be48bf7b,0xbf7b3e483e483f7b,0xbf75be95be953f75,0x3f753e953e95bf75,0x3ec4bf6dbf6dbec4,0xbec43f6d3f6d3ec4,0xbf463f223f223f46,0x3f46bf22bf22bf46,
0x3ef1bf623f623ef1,0xbef13f62bf62bef1,0x3e483f7bbf7b3e48,0xbe48bf7b3f7bbe48,0xbf46bf223f22bf46,0x3f463f22bf223f46,0x3f800000bf003f00,0x3f35bf353f353f35,
0xbdc93f7fbf7fbdc9,0x3dc9bf7f3f7f3dc9,0xbf0ebf553f55bf0e,0x3f0e3f55bf553f0e,0x3f753e95be953f75,0xbf75be953e95bf75,0xbf6d3ec4bec4bf6d,0x3f6dbec43ec43f6d,
0x3f6d3ec43ec4bf6d,0xbf6dbec4bec43f6d,0xbe95bf75bf753e95,0x3e953f753f75be95,0xbf0e3f553f553f0e,0x3f0ebf55bf55bf0e,0x3f7fbdc9bdc9bf7f,0xbf7f3dc93dc93f7f,
0xbf800000bf003f00,0xbf35bf35bf353f35,0x3f223f463f46bf22,0xbf22bf46bf463f22,0x3e48bf7bbf7bbe48,0xbe483f7b3f7b3e48,0xbf623ef13ef13f62,0x3f62bef1bef1bf62,
0xbf223f46bf46bf22,0x3f22bf463f463f22,0xbec4bf6d3f6dbec4,0x3ec43f6dbf6d3ec4,0xbe95bf753f75be95,0x3e953f75bf753e95,0x3f7b3e48be483f7b,0xbf7bbe483e48bf7b,
0xbef1bf623f62bef1,0x3ef13f62bf623ef1,0x3f800000bf003f00,0xbf353f35bf35bf35,0x3f7f3dc9bdc93f7f,0xbf7fbdc93dc9bf7f,0xbf0e3f55bf55bf0e,0x3f0ebf553f553f0e,
0xbe48bf7bbf7b3e48,0x3e483f7b3f7bbe48,0xbf623ef13ef13f62,0x3f62bef1bef1bf62,0xbec43f6d3f6d3ec4,0x3ec4bf6dbf6dbec4,0x3f7f3dc93dc9bf7f,0xbf7fbdc9bdc93f7f,
0x3f55bf0ebf0ebf55,0xbf553f0e3f0e3f55,0xbf46bf22bf223f46,0x3f463f223f22bf46,0xbf800000bf003f00,0x3f353f353f35bf35,0x3e953f753f75be95,0xbe95bf75bf753e95,
0x3f223f46bf463f22,0xbf22bf463f46bf22,0xbf553f0ebf0ebf55,0x3f55bf0e3f0e3f55,0xbef1bf623f62bef1,0x3ef13f62bf623ef1,0x3f6dbec43ec43f6d,0xbf6d3ec4bec4bf6d,
0x3e953f75bf753e95,0xbe95bf753f75be95,0xbf7b3e48be48bf7b,0x3f7bbe483e483f7b,0xbdc9bf7f3f7fbdc9,0x3dc93f7fbf7f3dc9,0x3f800000bf003f00,0x3f35bf353f353f35,
0x80003f803f003f00,0x80003f8080003f80,0x3f8000003f800000,0x3f8000003f800000,0x8000bf808000bf80,0x8000bf808000bf80,0xbf800000bf800000,0xbf800000bf800000,
0x80003f8080003f80,0x80003f8080003f80,0x3f8000003f800000,0x3f8000003f800000,0x8000bf808000bf80,0x8000bf808000bf80,0xbf800000bf800000,0xbf800000bf800000,
0xbf7bbe483f7b3e48,0xbf7bbe483f7b3e48,0x8000bf803f003f00,0x3f800000bf800000,0x3f553f0ebf55bf0e,0x3f553f0ebf55bf0e,0xbec43f6d3ec4bf6d,0xbec43f6d3ec4bf6d,
0xbf0ebf553f0e3f55,0xbf0ebf553f0e3f55,0x3f35bf35bf353f35,0x3f35bf35bf353f35,0x3e483f7bbe48bf7b,0x3e483f7bbe48bf7b,0xbf6d3ec43f6dbec4,0xbf6d3ec43f6dbec4,
0x3f35bf353f35bf35,0x3f35bf353f35bf35,0xbec4bf6dbec4bf6d,0xbec4bf6dbec4bf6d,0x80003f803f003f00,0x8000bf808000bf80,0x3f6d3ec43f6d3ec4,0x3f6d3ec43f6d3ec4,
0x3f353f353f353f35,0x3f353f353f353f35,0x3f6dbec43f6dbec4,0x3f6dbec43f6dbec4,0xbf800000bf800000,0xbf800000bf800000,0xbec43f6dbec43f6d,0xbec43f6dbec43f6d,
0xbe483f7b3e48bf7b,0xbe483f7b3e48bf7b,0xbf6d3ec43f6dbec4,0xbf6d3ec43f6dbec4,0xbf55bf0e3f553f0e,0xbf55bf0e3f553f0e,0x8000bf803f003f00,0xbf8000003f800000,
0xbf0ebf553f0e3f55,0xbf0ebf553f0e3f55,0x3ec4bf6dbec43f6d,0x3ec4bf6dbec43f6d,0x3f7bbe48bf7b3e48,0x3f7bbe48bf7b3e48,0x3f353f35bf35bf35,0x3f353f35bf35bf35,
0x8000bf808000bf80,0x8000bf808000bf80,0xbf35bf35bf35bf35,0xbf35bf35bf35bf35,0xbf800000bf800000,0xbf800000bf800000,0xbf353f35bf353f35,0xbf353f35bf353f35,
0x80003f803f003f00,0x80003f8080003f80,0x3f353f353f353f35,0x3f353f353f353f35,0x3f8000003f800000,0x3f8000003f800000,0x3f35bf353f35bf35,0x3f35bf353f35bf35,
0xbe483f7b3e48bf7b,0xbe483f7b3e48bf7b,0xbf353f353f35bf35,0xbf353f353f35bf35,0x3f553f0ebf55bf0e,0x3f553f0ebf55bf0e,0x3ec43f6dbec4bf6d,0x3ec43f6dbec4bf6d,
0xbf0ebf553f0e3f55,0xbf0ebf553f0e3f55,0x8000bf803f003f00,0x3f800000bf800000,0xbf7b3e483f7bbe48,0xbf7b3e483f7bbe48,0xbf6dbec43f6d3ec4,0xbf6dbec43f6d3ec4,
0x3f35bf353f35bf35,0x3f35bf353f35bf35,0x3ec4bf6d3ec4bf6d,0x3ec4bf6d3ec4bf6d,0x3f8000003f800000,0x3f8000003f800000,0x3f6dbec43f6dbec4,0x3f6dbec43f6dbec4,
0x3f353f353f353f35,0x3f353f353f353f35,0x3f6d3ec43f6d3ec4,0x3f6d3ec43f6d3ec4,0x80003f803f003f00,0x8000bf808000bf80,0x3ec43f6d3ec43f6d,0x3ec43f6d3ec43f6d,
0xbf7bbe483f7b3e48,0xbf7bbe483f7b3e48,0xbf6dbec43f6d3ec4,0xbf6dbec43f6d3ec4,0xbf55bf0e3f553f0e,0xbf55bf0e3f553f0e,0xbf35bf353f353f35,0xbf35bf353f353f35,
0xbf0ebf553f0e3f55,0xbf0ebf553f0e3f55,0xbec4bf6d3ec43f6d,0xbec4bf6d3ec43f6d,0xbe48bf7b3e483f7b,0xbe48bf7b3e483f7b,0x8000bf803f003f00,0xbf8000003f800000,
0xbf800000bf003f00,0xbf35bf35bf353f35,0xbdc93f7f3f7f3dc9,0x3dc9bf7fbf7fbdc9,0x3f7b3e483e48bf7b,0xbf7bbe48be483f7b,0x3e95bf75bf75be95,0xbe953f753f753e95,
0xbf6dbec4bec43f6d,0x3f6d3ec43ec4bf6d,0xbef13f623f623ef1,0x3ef1bf62bf62bef1,0x3f553f0e3f0ebf55,0xbf55bf0ebf0e3f55,0x3f22bf46bf46bf22,0xbf223f463f463f22,
0x3e95bf753f753e95,0xbe953f75bf75be95,0x3f800000bf003f00,0xbf353f35bf35bf35,0xbf463f22bf22bf46,0x3f46bf223f223f46,0xbf55bf0e3f0ebf55,0x3f553f0ebf0e3f55,
0x3f7fbdc93dc93f7f,0xbf7f3dc9bdc9bf7f,0x3ec43f6dbf6d3ec4,0xbec4bf6d3f6dbec4,0xbf62bef13ef1bf62,0x3f623ef1bef13f62,0x3e48bf7b3f7b3e48,0xbe483f7bbf7bbe48,
0x3f0e3f553f55bf0e,0xbf0ebf55bf553f0e,0x3f7fbdc9bdc9bf7f,0xbf7f3dc93dc93f7f,0xbf800000bf003f00,0x3f353f353f35bf35,0xbef13f623f623ef1,0x3ef1bf62bf62bef1,
0xbf7b3e483e483f7b,0x3f7bbe48be48bf7b,0xbe953f753f753e95,0x3e95bf75bf75be95,0x3ec4bf6dbf6dbec4,0xbec43f6d3f6d3ec4,0xbf22bf46bf463f22,0x3f223f463f46bf22,
0xbf62bef13ef1bf62,0x3f623ef1bef13f62,0xbe48bf7b3f7bbe48,0x3e483f7bbf7b3e48,0x3f22bf463f463f22,0xbf223f46bf46bf22,0x3f800000bf003f00,0x3f35bf353f353f35,
0x3f7f3dc9bdc93f7f,0xbf7fbdc93dc9bf7f,0x3f0e3f55bf553f0e,0xbf0ebf553f55bf0e,0xbe953f75bf75be95,0x3e95bf753f753e95,0xbf6d3ec4bec4bf6d,0x3f6dbec43ec43f6d,
0x3f6d3ec43ec4bf6d,0xbf6dbec4bec43f6d,0x3f75be95be95bf75,0xbf753e953e953f75,0x3f0ebf55bf55bf0e,0xbf0e3f553f553f0e,0xbdc9bf7fbf7f3dc9,0x3dc93f7f3f7fbdc9,
0xbf800000bf003f00,0xbf35bf35bf353f35,0xbf463f223f223f46,0x3f46bf22bf22bf46,0xbe483f7b3f7b3e48,0x3e48bf7bbf7bbe48,0x3ef13f623f62bef1,0xbef1bf62bf623ef1,
0xbf46bf223f22bf46,0x3f463f22bf223f46,0xbec4bf6d3f6dbec4,0x3ec43f6dbf6d3ec4,0xbf753e95be95bf75,0x3f75be953e953f75,0xbf7bbe483e48bf7b,0x3f7b3e48be483f7b,
0x3f62bef13ef13f62,0xbf623ef1bef1bf62,0x3f800000bf003f00,0xbf353f35bf35bf35,0x3dc9bf7f3f7f3dc9,0xbdc93f7fbf7fbdc9,0x3f0ebf553f553f0e,0xbf0e3f55bf55bf0e,
0x3e483f7b3f7bbe48,0xbe48bf7bbf7b3e48,0x3ef13f623f62bef1,0xbef1bf62bf623ef1,0xbec43f6d3f6d3ec4,0x3ec4bf6dbf6dbec4,0xbdc93f7f3f7f3dc9,0x3dc9bf7fbf7fbdc9,
0xbf553f0e3f0e3f55,0x3f55bf0ebf0ebf55,0xbf223f463f463f22,0x3f22bf46bf46bf22,0xbf800000bf003f00,0x3f353f353f35bf35,0xbf753e953e953f75,0x3f75be95be95bf75,
0x3f46bf223f223f46,0xbf463f22bf22bf46,0x3f55bf0e3f0e3f55,0xbf553f0ebf0ebf55,0x3f62bef13ef13f62,0xbf623ef1bef1bf62,0x3f6dbec43ec43f6d,0xbf6d3ec4bec4bf6d,
0x3f75be953e953f75,0xbf753e95be95bf75,0x3f7bbe483e483f7b,0xbf7b3e48be48bf7b,0x3f7fbdc93dc93f7f,0xbf7f3dc9bdc9bf7f,0x3f800000bf003f00,0x3f35bf353f353f35,
0x80003f808000bf80,0x3ec4bf6d8000bf80,0x80003f808000bf80,0x3f6d3ec48000bf80,0x80003f808000bf80,0xbec43f6d8000bf80,0x80003f808000bf80,0xbf6dbec48000bf80,
0x80003f808000bf80,0x3ec4bf6d8000bf80,0x80003f808000bf80,0x3f6d3ec48000bf80,0x80003f808000bf80,0xbec43f6d8000bf80,0x80003f808000bf80,0xbf6dbec48000bf80,
0xbe953f753e79bf78,0x3f4e3f183eacbf71,0xbdc93f7f3d49bf80,0x3edbbf673e16bf7d,0xbf223f463f18bf4e,0xbf04bf5c3f2cbf3e,0xbef13f623edbbf67,0xbf3e3f2c3f04bf5c,
0xbf623ef13f5cbf04,0x3e163f7d3f67bedb,0xbf463f223f3ebf2c,0x3f71beac3f4ebf18,0xbf7f3dc93f7dbe16,0x3e79bf783f80bd49,0xbf753e953f71beac,0xbf80bd493f78be79,
0xbf553f0e3f46bf22,0xbf753e953f62bef1,0xbf7b3e483f75be95,0x3dc9bf7f3f7fbdc9,0xbe483f7b3dc9bf7f,0x3ef1bf623e95bf75,0xbf0e3f553ef1bf62,0x3f223f463f22bf46,
0xbf0ebf553f223f46,0xbe95bf753ef13f62,0xbe48bf7b3e953f75,0x3f7f3dc93dc93f7f,0xbf7bbe483f7f3dc9,0x3f623ef13f753e95,0xbf55bf0e3f623ef1,0xbf463f223f463f22,
0xbf62bef13f713eac,0x3f2cbf3e3f4e3f18,0xbf7f3dc93f78be79,0xbf7dbe163f803d49,0xbf463f223f2cbf3e,0x3edb3f673f5cbf04,0xbe953f753e16bf7d,0x3f04bf5c3edbbf67,
0x3f75be95bf673edb,0x3d493f80bf7d3e16,0x3f22bf46bf043f5c,0x3f4ebf18bf3e3f2c,0x3dc9bf7f3d493f80,0xbf71beacbe793f78,0xbef1bf623f183f4e,0x3e793f783eac3f71,
0x3ec4bf6dbe483f7b,0xbf0e3f55bf0e3f55,0x3f6dbec4bf553f0e,0xbe48bf7bbf7b3e48,0x3f6d3ec4bf7bbe48,0x3f553f0ebf55bf0e,0x3ec43f6dbf0ebf55,0xbf7b3e48be48bf7b,
0xbec43f6d3e48bf7b,0x3f0ebf553f0ebf55,0xbf6d3ec43f55bf0e,0x3e483f7b3f7bbe48,0xbf6dbec43f7b3e48,0xbf55bf0e3f553f0e,0xbec4bf6d3f0e3f55,0x3f7bbe483e483f7b,
0x3f463f22bf67bedb,0x3f3ebf2cbf18bf4e,0x3f75be95bf5c3f04,0xbf7d3e16bf803d49,0xbf623ef13f3ebf2c,0xbeacbf713f78be79,0xbdc93f7fbe16bf7d,0xbe793f783eacbf71,
0xbf7f3dc93f71beac,0xbd493f803f7d3e16,0xbef13f623e79bf78,0x3f18bf4e3f2cbf3e,0x3e95bf75bd493f80,0x3f673edbbf043f5c,0xbf22bf463f4e3f18,0xbf04bf5c3edb3f67,
0xbf7b3e483f62bef1,0xbf7f3dc93f7f3dc9,0xbf0ebf553f463f22,0x3f62bef13e953f75,0x3f553f0ebf75be95,0xbf46bf22bf22bf46,0xbe483f7bbdc9bf7f,0x3f753e953ef1bf62,
0xbe48bf7b3ef13f62,0xbdc9bf7fbdc93f7f,0x3f55bf0ebf223f46,0x3ef13f62bf753e95,0xbf0e3f553e95bf75,0x3f22bf463f46bf22,0xbf7bbe483f7fbdc9,0xbe953f753f623ef1,
0x3f46bf22bf043f5c,0x3f183f4ebf713eac,0xbef1bf623f3e3f2c,0xbedbbf673e163f7d,0xbf753e953f4ebf18,0x3e793f783f803d49,0x3dc93f7fbedbbf67,0xbd49bf803e79bf78,
0x3f7f3dc9bf783e79,0xbe163f7dbf67bedb,0x3e95bf753d493f80,0x3eacbf71bf183f4e,0xbf62bef13f7d3e16,0xbf043f5c3f2c3f3e,0xbf223f463eacbf71,0x3f2cbf3e3f5cbf04,
0xbd493f803cc9bf80,0x3ecfbf6a3d97bf7f,0xbe163f7d3dfbbf7e,0x3f5f3efc3e2fbf7c,0xbe793f783e60bf7a,0xbf133f513e89bf77,0xbeac3f713ea1bf73,0xbf42bf273eb8bf6f,
0xbedb3f673ecfbf6a,0x3f39bf313ee6bf65,0xbf043f5c3efcbf5f,0x3f1d3f4a3f09bf58,0xbf183f4e3f13bf51,0xbf583f093f1dbf4a,0xbf2c3f3e3f27bf42,0xbee6bf653f31bf39,
0xbedb3f673eb8bf6f,0x3f393f313efcbf5f,0xbe163f7d3d97bf7f,0x3ee6bf653e60bf7a,0xbf5c3f043f51bf13,0xbe60bf7a3f65bee6,0xbf2c3f3e3f1dbf4a,0xbf5f3efc3f39bf31,
0xbf80bd493f80bcc9,0xbeb83f6f3f7e3dfb,0xbf783e793f73bea1,0x3f7f3d973f7cbe2f,0xbf4ebf183f583f09,0x3f51bf133f423f27,0xbf71beac3f773e89,0xbf4abf1d3f6a3ecf,
0xbf713eac3f65bee6,0xbf7f3d973f7abe60,0xbf7dbe163f803cc9,0x3ecfbf6a3f773e89,0xbe793f783dfbbf7e,0x3efcbf5f3eb8bf6f,0xbf2c3f3e3f13bf51,0x3f093f583f42bf27,
0x3d49bf803d973f7f,0x3ea1bf73be2f3f7c,0x3f04bf5cbecf3f6a,0x3f313f39bf1d3f4a,0xbf4ebf183f5f3efc,0x3f1d3f4a3f393f31,0xbedbbf673f093f58,0xbf7c3e2f3ea13f73,
0xbf2cbf3e3f4a3f1d,0x3f5fbefc3f093f58,0xbf7dbe163f80bcc9,0xbf6fbeb83f733ea1,0xbf5c3f043f42bf27,0x3ea13f733f6fbeb8,0xbeac3f713e2fbf7c,0x3f09bf583efcbf5f,
0x3f673edbbf77be89,0xbf1d3f4abf51bf13,0x3f78be79bf6a3ecf,0x3f80bcc9bf7f3d97,0x3f18bf4ebee63f65,0xbf27bf42bf393f31,0xbd49bf803e603f7a,0xbe2f3f7cbdfb3f7e,
0x3f3ebf2cbf133f51,0xbf583f09bf5f3efc,0x3f7d3e16bf7f3d97,0x3ea1bf73bf6fbeb8,0x3f043f5cbf31bf39,0x3eb83f6fbea1bf73,0xbeac3f713dfbbf7e,0xbf5fbefc3f09bf58,
0xbedb3f673e60bf7a,0x3f13bf513f1dbf4a,0xbf783e793f65bee6,0x3d973f7f3f80bcc9,0xbf4ebf183f6a3ecf,0xbf31bf393f273f42,0xbd49bf803e893f77,0x3f7e3dfbbe2f3f7c,
0x3eac3f71bf13bf51,0x3f7abe60bd97bf7f,0x3f7d3e16bf7e3dfb,0xbf77be89bf6abecf,0xbf78be793f80bcc9,0x3eb8bf6f3f5f3efc,0xbf2c3f3e3ee6bf65,0xbf423f273f58bf09,
0xbf80bd493f7abe60,0xbe2f3f7c3f733ea1,0xbf043f5c3e89bf77,0x3f1dbf4a3f39bf31,0x3f18bf4ebeb83f6f,0x3f393f31bf4a3f1d,0xbedbbf673f273f42,0xbea1bf733e2f3f7c,
0xbf67bedb3f7e3dfb,0xbf5fbefc3f393f31,0x3e16bf7d3e2f3f7c,0x3f7a3e60bee63f65,0x3f043f5cbf42bf27,0xbee6bf65be60bf7a,0xbf2c3f3e3ecfbf6a,0x3f313f393f5fbefc,
0x3d49bf803e893f77,0x3dfbbf7ebeb83f6f,0x3f78be79bf583f09,0x3e2f3f7cbf7fbd97,0xbf183f4e3ea1bf73,0x3f27bf423f51bf13,0xbf71beac3f803cc9,0xbecf3f6a3f4a3f1d,
0x3f803d49bf733ea1,0xbd973f7fbf6abecf,0x3e16bf7d3e603f7a,0x3e2fbf7cbefc3f5f,0xbf78be793f7ebdfb,0xbe893f773f513f13,0xbeac3f71bcc9bf80,0x3eb8bf6f3f27bf42,
0x3f673edbbf7fbd97,0xbee63f65bf31bf39,0x3f04bf5cbe2f3f7c,0x3f09bf58bf4a3f1d,0xbf4ebf183f773e89,0xbf1d3f4a3f093f58,0xbf2c3f3e3eb8bf6f,0x3f31bf393f65bee6,
0x3f6dbec4bf353f35,0xbf8000003f35bf35,0x3ec43f6dbf35bf35,0x3f800000bf353f35,0xbf6d3ec43f35bf35,0xbf8000003f35bf35,0xbec4bf6d3f353f35,0x3f800000bf353f35,
0x3f6dbec4bf353f35,0xbf8000003f35bf35,0x3ec43f6dbf35bf35,0x3f800000bf353f35,0xbf6d3ec43f35bf35,0xbf8000003f35bf35,0xbec4bf6d3f353f35,0x3f800000bf353f35,
0x3d493f80bef1bf62,0x3f753e95bf5c3f04,0x3f78be79bf463f22,0xbf7fbdc93f3ebf2c,0x3eacbf713dc93f7f,0x3f463f22bf7d3e16,0xbf7dbe163f75be95,0xbf62bef13f71beac,
0xbf2c3f3e3e95bf75,0x3ef13f62bf78be79,0x3f5c3f04bf7fbdc9,0xbf22bf463f803d49,0x3f67bedbbf223f46,0x3dc93f7fbf4ebf18,0xbf18bf4e3f623ef1,0xbe95bf753f673edb,
0xbf46bf223f7b3e48,0xbf0ebf553f7f3dc9,0x3f62bef1bf0e3f55,0x3e483f7bbf62bef1,0x3f7fbdc9bf553f0e,0xbf7bbe483f46bf22,0xbe953f75be48bf7b,0x3f553f0ebf753e95,
0x3f22bf46be483f7b,0x3f55bf0ebdc93f7f,0x3ef13f62bf55bf0e,0xbf7b3e483ef1bf62,0x3dc93f7fbf0ebf55,0x3e48bf7b3f223f46,0xbf75be953f7bbe48,0xbf0e3f55be95bf75,
0x3f783e79bf753e95,0xbef13f62bedbbf67,0xbeacbf713f463f22,0xbdc9bf7f3f5c3f04,0xbf183f4e3dc9bf7f,0x3f223f46bf803d49,0x3f803d49bf623ef1,0xbf75be953f4ebf18,
0xbf5c3f043ef1bf62,0xbe95bf753f713eac,0x3f673edbbf7f3dc9,0x3f463f22bf783e79,0xbe16bf7d3f223f46,0xbf7fbdc93f2cbf3e,0xbf3e3f2c3e95bf75,0x3f62bef1be163f7d,
0xbf7bbe483f6dbec4,0x3f6d3ec4bf553f0e,0x3f55bf0ebec43f6d,0xbec4bf6d3f7b3e48,0xbe483f7bbec4bf6d,0xbec43f6dbf0ebf55,0xbf0ebf553f6d3ec4,0x3f6dbec4be483f7b,
0x3f7b3e48bf6d3ec4,0xbf6dbec43f55bf0e,0xbf553f0e3ec4bf6d,0x3ec43f6dbf7bbe48,0x3e48bf7b3ec43f6d,0x3ec4bf6d3f0e3f55,0x3f0e3f55bf6dbec4,0xbf6d3ec43e48bf7b,
0x3f5c3f04bf7f3dc9,0x3f22bf463eac3f71,0xbedbbf673f623ef1,0x3e953f75bf78be79,0x3f4ebf18be953f75,0x3ef13f62bf80bd49,0xbf803d493f46bf22,0xbf7fbdc93f18bf4e,
0xbf783e793f22bf46,0x3dc93f7fbf67bedb,0x3f713eacbf753e95,0xbf62bef13f5cbf04,0xbe163f7dbef1bf62,0xbf75be953f3ebf2c,0x3f2cbf3ebdc93f7f,0x3f46bf223e163f7d,
0xbe95bf753f553f0e,0xbe48bf7b3f753e95,0x3f223f46bf7bbe48,0xbf553f0ebdc9bf7f,0x3ef1bf623e483f7b,0xbf0e3f55bef1bf62,0xbdc93f7fbf0ebf55,0x3f7b3e48bf223f46,
0x3f75be95bf0e3f55,0x3f7bbe48be953f75,0xbf463f223e48bf7b,0xbf0ebf553f7fbdc9,0x3f623ef1bf7b3e48,0xbf55bf0e3f62bef1,0xbf7fbdc93f55bf0e,0xbe483f7bbf46bf22,
0xbf3e3f2c3dc9bf7f,0xbf22bf463f78be79,0x3f5cbf04be953f75,0x3f62bef13d493f80,0xbf713eac3ef1bf62,0x3e953f75bf7dbe16,0x3f7dbe16bf223f46,0xbf7f3dc93eacbf71,
0xbf80bd493f46bf22,0x3dc9bf7f3f5c3f04,0x3f783e79bf623ef1,0x3f753e95bf2c3f3e,0xbf67bedb3f75be95,0xbef13f62bf18bf4e,0x3f4e3f18bf7f3dc9,0xbf46bf223f67bedb,
0x3f73bea1bf3e3f2c,0xbf80bd493f39bf31,0x3e603f7abf18bf4e,0x3f7d3e16bf4a3f1d,0xbf7e3dfb3f5cbf04,0xbf78be793f58bf09,0xbcc9bf803edb3f67,0x3f713eacbf653ee6,
0x3f7f3d97bf713eac,0xbf67bedb3f6fbeb8,0xbe2f3f7cbe79bf78,0x3f5c3f04bf773e89,0xbf77be893f7dbe16,0xbf4ebf183f7cbe2f,0x3eb8bf6f3d493f80,0x3f3e3f2cbf7f3d97,
0xbdfb3f7ebeacbf71,0x3f673edbbf6a3ecf,0x3f7cbe2fbf4e3f18,0xbf7dbe163f42bf27,0x3f27bf42be793f78,0x3f043f5cbf7cbe2f,0xbf6abecf3f80bd49,0xbf3ebf2c3f7ebdfb,
0xbf773e893f3ebf2c,0xbd493f80bf39bf31,0x3f093f58bf5cbf04,0xbe79bf783f653ee6,0x3f733ea1bf7d3e16,0xbf183f4ebe60bf7a,0x3cc9bf803edb3f67,0x3eacbf713efc3f5f,
0xbf13bf513f673edb,0xbeacbf713f733ea1,0x3f7ebdfbbf4e3f18,0xbe163f7dbf31bf39,0x3f80bcc9bf5c3f04,0xbf78be793f4abf1d,0xbee63f65bd49bf80,0x3f3e3f2cbf7c3e2f,
0x3f7abe60bf3e3f2c,0x3f803d49bf273f42,0xbe893f77be79bf78,0xbf5cbf043f6fbeb8,0xbeb83f6fbe16bf7d,0x3f18bf4e3e893f77,0xbf27bf423f713eac,0xbf673edb3e60bf7a,
0x3f513f13bf80bd49,0xbf3e3f2cbdfbbf7e,0xbd97bf7f3f183f4e,0x3e16bf7d3f393f31,0xbf393f313e79bf78,0x3f043f5cbf7fbd97,0x3f7e3dfbbf673edb,0xbf71beac3f51bf13,
0xbf7abe603f71beac,0x3edbbf673efc3f5f,0x3ee63f65bf5cbf04,0x3e793f78bf6fbeb8,0x3ecfbf6a3e163f7d,0xbf4ebf183f73bea1,0xbf773e893f2cbf3e,0x3f80bd49bf093f58,
0xbf4abf1d3f803d49,0x3f2c3f3ebf7c3e2f,0x3f80bcc9bf4e3f18,0x3e16bf7d3f423f27,0xbf423f273e79bf78,0xbf5c3f043cc9bf80,0x3e2fbf7c3edb3f67,0x3f713eacbf4a3f1d,
0x3f773e89bf713eac,0xbf67bedb3f58bf09,0xbf6a3ecf3f04bf5c,0x3e793f78bf73bea1,0x3ee6bf653e163f7d,0x3f18bf4e3eb83f6f,0x3e603f7abf3ebf2c,0xbf803d493efcbf5f,
0x3ee63f65bf67bedb,0x3f71beacbe2f3f7c,0x3cc9bf803f183f4e,0xbe163f7dbf4abf1d,0x3f7e3dfbbf5c3f04,0xbe793f78bf39bf31,0xbf51bf133f80bd49,0xbf3ebf2c3f73bea1,
0xbf7f3d973f3ebf2c,0xbd493f80bf58bf09,0x3f6a3ecfbf783e79,0xbf5cbf043f5fbefc,0xbefc3f5fbe16bf7d,0xbf4ebf183f6abecf,0x3f58bf09beac3f71,0x3f67bedbbd973f7f,
0x3eb8bf6f3eac3f71,0x3edbbf673f1d3f4a,0xbd973f7fbf18bf4e,0xbf7dbe163f13bf51,0x3f51bf13be793f78,0xbf5c3f04bd97bf7f,0xbf1d3f4abd49bf80,0x3f3e3f2cbf6f3eb8,
0x3f80bcc9bf3e3f2c,0x3f803d49befc3f5f,0xbf733ea13f04bf5c,0xbe79bf783f7a3e60,0x3f583f09bf7d3e16,0xbf4ebf183f65bee6,0xbf77be893f67bedb,0xbeac3f71bf31bf39,
0xbf80bcc93f3ebf2c,0x3d49bf803f653ee6,0x3f7e3dfbbf4e3f18,0x3f7d3e16bf093f58,0xbf7abe603f5cbf04,0xbe793f78bf4abf1d,0x3f733ea1bf673edb,0xbf71beac3f31bf39,
0xbf6abecf3f71beac,0x3edbbf673f273f42,0x3f5f3efcbf783e79,0x3f5c3f04bf513f13,0xbf51bf133f7dbe16,0xbf183f4ebefcbf5f,0x3f423f27bf803d49,0xbf3ebf2c3f6abecf,
0x3f6dbec43f353f35,0xbec43f6dbf35bf35,0xbec4bf6dbf35bf35,0x3f6d3ec4bf353f35,0xbf6d3ec43f353f35,0x3ec4bf6d3f353f35,0x3ec43f6dbf35bf35,0xbf6dbec43f35bf35,
0x3f6dbec43f353f35,0xbec43f6dbf35bf35,0xbec4bf6dbf35bf35,0x3f6d3ec4bf353f35,0xbf6d3ec43f353f35,0x3ec4bf6d3f353f35,0x3ec43f6dbf35bf35,0xbf6dbec43f35bf35,
0xbe16bf7dbedbbf67,0x3f3e3f2cbf623ef1,0x3f71beac3f183f4e,0xbf043f5cbf22bf46,0xbe793f78bd49bf80,0xbedbbf673f7fbdc9,0xbf80bd493e793f78,0x3f4ebf183e953f75,
0x3f18bf4e3eacbf71,0x3d493f80bf75be95,0x3f673edbbe163f7d,0xbf783e793dc9bf7f,0xbf5c3f043f2cbf3e,0x3eacbf713f463f22,0xbf2cbf3ebf043f5c,0x3f7d3e16bef13f62,
0xbf62bef1be953f75,0x3f7fbdc9be483f7b,0xbf463f223f22bf46,0x3e95bf753f553f0e,0x3f75be953ef13f62,0xbf223f46bf0ebf55,0x3dc9bf7fbdc9bf7f,0x3ef13f62bf7b3e48,
0x3ef1bf62bf75be95,0x3dc93f7fbf7bbe48,0xbf22bf463f463f22,0x3f753e95bf0e3f55,0x3e953f75bf623ef1,0xbf46bf223f55bf0e,0x3f7f3dc93f7fbdc9,0xbf623ef1be48bf7b,
0xbf803d493f7dbe16,0x3f5cbf043e953f75,0xbf18bf4ebf3e3f2c,0x3f673edbbf223f46,0x3eacbf713e79bf78,0x3e163f7dbf7fbdc9,0x3f78be793eac3f71,0xbf3e3f2cbef1bf62,
0x3f2cbf3ebf183f4e,0xbe793f78bf62bef1,0x3f7d3e163d49bf80,0xbf713eacbdc9bf7f,0x3edb3f673f043f5c,0xbf4ebf183f46bf22,0xbf043f5cbf67bedb,0x3d49bf803f753e95,
0xbf7b3e48be48bf7b,0x3f55bf0e3ec43f6d,0xbf0e3f55bf0e3f55,0x3e48bf7b3f6d3ec4,0x3e483f7b3f7bbe48,0xbf0ebf553f6dbec4,0x3f553f0ebf55bf0e,0xbf7bbe483ec4bf6d,
0x3f7bbe483e483f7b,0xbf553f0ebec4bf6d,0x3f0ebf553f0ebf55,0xbe483f7bbf6dbec4,0xbe48bf7bbf7b3e48,0x3f0e3f55bf6d3ec4,0xbf55bf0e3f553f0e,0x3f7b3e48bec43f6d,
0xbf80bd49bf7dbe16,0x3f78be793dc93f7f,0xbf4ebf183f2cbf3e,0x3f713eacbef13f62,0xbedb3f673f04bf5c,0x3e16bf7d3f753e95,0xbf5c3f043edb3f67,0x3f2cbf3e3f223f46,
0x3f3ebf2c3f4ebf18,0xbf043f5cbf46bf22,0x3f7dbe163d493f80,0xbf673edbbe95bf75,0xbeacbf713e793f78,0x3f183f4ebf623ef1,0x3e79bf78bf71beac,0x3d493f80bf7fbdc9,
0xbf46bf22bf463f22,0x3f623ef1bf0e3f55,0xbf75be953f623ef1,0x3f7f3dc9be483f7b,0xbdc9bf7f3f7f3dc9,0x3e953f75bf7b3e48,0xbef1bf62be95bf75,0x3f223f46bf553f0e,
0x3f22bf46bf22bf46,0xbef13f62bf55bf0e,0x3e95bf75bef13f62,0xbdc93f7fbf7bbe48,0x3f7fbdc9bdc93f7f,0xbf753e95be48bf7b,0x3f62bef13f75be95,0xbf463f22bf0ebf55,
0x3e16bf7dbedb3f67,0xbd493f80bf7fbdc9,0x3eacbf71bf4ebf18,0xbe793f78bf75be95,0x3f04bf5c3f3ebf2c,0xbedb3f67bf62bef1,0x3f2cbf3e3f043f5c,0xbf183f4ebf46bf22,
0x3f4ebf18bf713eac,0xbf3e3f2cbf22bf46,0x3f67bedbbe16bf7d,0xbf5c3f04bef1bf62,0x3f78be793f803d49,0xbf713eacbe95bf75,0x3f80bd49be793f78,0xbf7d3e16bdc9bf7f,
0x3f6fbeb83f273f42,0xbee63f65bf2cbf3e,0xbe89bf77bf13bf51,0x3f583f09bf4e3f18,0xbf7c3e2f3efc3f5f,0x3f1dbf4a3f043f5c,0x3d973f7fbecfbf6a,0xbf39bf313f67bedb,
0x3f803cc93ea13f73,0xbf423f27beacbf71,0x3dfbbf7ebe60bf7a,0x3f133f51bf783e79,0xbf7abe603dfb3f7e,0x3f5fbefc3e163f7d,0xbea13f73bcc9bf80,0xbecfbf6a3f80bd49,
0xbcc9bf80be89bf77,0x3f1d3f4abf713eac,0x3f73bea13f093f58,0xbf133f51bf18bf4e,0xbf093f583ea1bf73,0xbd97bf7f3f783e79,0xbf77be89bcc93f80,0x3f6fbeb83d493f80,
0x3f6abecf3f4abf1d,0xbefc3f5fbf2cbf3e,0x3f273f42bf133f51,0xbf7abe603f04bf5c,0xbf7cbe2f3f7fbd97,0x3f65bee63e163f7d,0xbdfbbf7ebf6f3eb8,0x3f313f39bf673edb,
0xbf42bf27bf093f58,0x3f7c3e2fbedb3f67,0xbf6f3eb83f5fbefc,0x3f1dbf4a3f183f4e,0x3f77be893ecf3f6a,0xbf313f39bf04bf5c,0x3e60bf7a3d97bf7f,0x3ea13f73bf803d49,
0x3f65bee6bf13bf51,0xbf093f58bf2cbf3e,0x3cc9bf803dfb3f7e,0x3efc3f5fbf783e79,0xbdfb3f7ebf803cc9,0xbecfbf6a3f7dbe16,0x3f513f133f653ee6,0xbf7fbd973eacbf71,
0xbf77be893f7a3e60,0x3f7cbe2fbd493f80,0xbecfbf6abf653ee6,0x3f423f27bf4e3f18,0x3ee6bf653ecfbf6a,0xbcc93f80bf78be79,0x3f7abe603e893f77,0xbf4a3f1dbedbbf67,
0x3f7ebdfbbf7c3e2f,0xbf583f09beacbf71,0x3f393f313f27bf42,0xbf73bea13f04bf5c,0xbd973f7fbcc93f80,0xbeb8bf6f3f7dbe16,0xbf513f13bf1dbf4a,0x3efcbf5f3f3e3f2c,
0xbf7abe603e89bf77,0x3f7ebdfbbd493f80,0xbf653ee6bf6a3ecf,0x3f31bf393f183f4e,0xbecf3f6a3f653ee6,0x3d97bf7f3f783e79,0x3e893f77be60bf7a,0xbf13bf513f67bedb,
0x3f7cbe2f3dfb3f7e,0xbf5f3efcbeacbf71,0x3f27bf423f31bf39,0xbeb83f6fbf5cbf04,0x3cc9bf80bf7fbd97,0x3ea13f73bf7d3e16,0xbf1dbf4a3f133f51,0x3f583f09bf2c3f3e,
0xbf58bf09bf42bf27,0x3f733ea1bedb3f67,0xbefcbf5f3f6fbeb8,0x3f313f39bf4e3f18,0xbf6a3ecf3f77be89,0x3f4abf1d3f043f5c,0xbf7fbd97be603f7a,0x3f7cbe2f3d493f80,
0x3f51bf133f65bee6,0xbf273f42bf2cbf3e,0x3f7ebdfbbcc93f80,0xbf6f3eb8be79bf78,0xbcc9bf80bdfb3f7e,0x3e893f77bf7d3e16,0x3ee6bf65bf51bf13,0xbe603f7abf71beac,
0xbe89bf77bf803cc9,0x3ecf3f6abf713eac,0xbf09bf583ea13f73,0x3f273f42bf4e3f18,0x3ea1bf733f583f09,0xbe2f3f7cbf78be79,0x3cc9bf803e89bf77,0x3dfb3f7ebf803d49,
0x3f4abf1dbecfbf6a,0xbf313f39bf2cbf3e,0x3f13bf51bf423f27,0xbee63f65bf5cbf04,0x3f7fbd97be2f3f7c,0xbf7a3e60be16bf7d,0x3f6fbeb83f7ebdfb,0xbf5f3efcbedbbf67,
0x3f42bf27bf6f3eb8,0xbf393f31bf2cbf3e,0x3f51bf13be89bf77,0xbf4a3f1dbf18bf4e,0x3f5fbefc3f7cbe2f,0xbf583f09bf04bf5c,0x3f6abecf3d973f7f,0xbf653ee6bedbbf67,
0x3f73bea1bf80bcc9,0xbf6f3eb8beacbf71,0x3f7abe603dfbbf7e,0xbf773e89be79bf78,0x3f7ebdfb3f7a3e60,0xbf7c3e2fbe16bf7d,0x3f80bcc9bea13f73,0xbf7f3d97bd49bf80,
0x8000bf803f800000,0x3f6d3ec4bf800000,0x8000bf803f800000,0xbec43f6dbf800000,0x8000bf803f800000,0xbf6dbec4bf800000,0x8000bf803f800000,0x3ec4bf6dbf800000,
0x8000bf803f800000,0x3f6d3ec4bf800000,0x8000bf803f800000,0xbec43f6dbf800000,0x8000bf803f800000,0xbf6dbec4bf800000,0x8000bf803f800000,0x3ec4bf6dbf800000,
0x3e95bf753f783e79,0xbf183f4ebf71beac,0x3dc9bf7f3f803d49,0x3f673edbbf7dbe16,0x3f22bf463f4e3f18,0x3f5cbf04bf3ebf2c,0x3ef1bf623f673edb,0xbf2cbf3ebf5cbf04,
0x3f62bef13f043f5c,0xbf7d3e16bedbbf67,0x3f46bf223f2c3f3e,0x3eac3f71bf18bf4e,0x3f7fbdc93e163f7d,0x3f783e79bd49bf80,0x3f75be953eac3f71,0x3d49bf80be79bf78,
0x3f55bf0e3f223f46,0xbe95bf75bef1bf62,0x3f7bbe483e953f75,0x3f7f3dc9bdc9bf7f,0x3e48bf7b3f7f3dc9,0x3f623ef1bf75be95,0x3f0ebf553f623ef1,0xbf463f22bf46bf22,
0x3f0e3f55bf463f22,0x3f75be953f62bef1,0x3e483f7bbf753e95,0xbdc93f7f3f7fbdc9,0x3f7b3e48bdc93f7f,0xbef13f623e95bf75,0x3f553f0ebef13f62,0xbf22bf463f22bf46,
0x3f623ef1beac3f71,0x3f3e3f2c3f18bf4e,0x3f7fbdc93e793f78,0x3e16bf7d3d49bf80,0x3f46bf223f3e3f2c,0xbf673edbbf04bf5c,0x3e95bf753f7d3e16,0x3f5c3f04bf67bedb,
0xbf753e95bedbbf67,0xbf803d493e163f7d,0xbf223f46bf5cbf04,0x3f183f4e3f2c3f3e,0xbdc93f7fbf803d49,0x3eacbf713f783e79,0x3ef13f62bf4e3f18,0xbf783e793f71beac,
0xbec43f6dbf7bbe48,0xbf55bf0e3f553f0e,0xbf6d3ec4bf0ebf55,0x3f7bbe483e483f7b,0xbf6dbec43e48bf7b,0xbf0e3f55bf0e3f55,0xbec4bf6d3f55bf0e,0xbe48bf7bbf7b3e48,
0x3ec4bf6d3f7b3e48,0x3f553f0ebf55bf0e,0x3f6dbec43f0e3f55,0xbf7b3e48be48bf7b,0x3f6d3ec4be483f7b,0x3f0ebf553f0ebf55,0x3ec43f6dbf553f0e,0x3e483f7b3f7bbe48,
0xbf46bf223edbbf67,0x3f2c3f3ebf4e3f18,0xbf753e95bf04bf5c,0xbe16bf7d3d493f80,0x3f62bef13f2c3f3e,0x3f71beacbe79bf78,0x3dc9bf7f3f7dbe16,0xbf78be79bf71beac,
0x3f7fbdc93eac3f71,0xbf80bd493e16bf7d,0x3ef1bf623f783e79,0x3f4e3f18bf3ebf2c,0xbe953f75bf80bd49,0xbedb3f673f5c3f04,0x3f223f46bf183f4e,0x3f5cbf043f67bedb,
0x3f7bbe483ef13f62,0xbdc9bf7f3dc9bf7f,0x3f0e3f55bf223f46,0x3ef13f623f75be95,0xbf55bf0e3e95bf75,0x3f22bf46bf463f22,0x3e48bf7b3f7fbdc9,0xbe953f75bf62bef1,
0x3e483f7bbf623ef1,0x3f7fbdc93f7f3dc9,0xbf553f0ebf46bf22,0xbf623ef13e953f75,0x3f0ebf553f753e95,0x3f463f22bf22bf46,0x3f7b3e483dc93f7f,0xbf75be953ef1bf62,
0xbf463f22bf5cbf04,0xbf4e3f183eac3f71,0x3ef13f62bf2c3f3e,0x3f67bedb3f7dbe16,0x3f75be953f183f4e,0xbf783e793d49bf80,0xbdc9bf7f3f67bedb,0x3f80bd49bf78be79,
0xbf7fbdc9be79bf78,0xbf7dbe16bedb3f67,0xbe953f75bf803d49,0x3f713eac3f4e3f18,0x3f623ef1be163f7d,0xbf5cbf043f3ebf2c,0x3f22bf463f713eac,0x3f3e3f2cbf04bf5c,
0x3d49bf803f803cc9,0x3f6a3ecfbf7fbd97,0x3e16bf7d3f7e3dfb,0xbefc3f5fbf7cbe2f,0x3e79bf783f7a3e60,0xbf51bf13bf77be89,0x3eacbf713f733ea1,0x3f27bf42bf6fbeb8,
0x3edbbf673f6a3ecf,0x3f313f39bf65bee6,0x3f04bf5c3f5f3efc,0xbf4a3f1dbf58bf09,0x3f18bf4e3f513f13,0xbf09bf58bf4abf1d,0x3f2cbf3e3f423f27,0x3f65bee6bf39bf31,
0x3edbbf673f6f3eb8,0xbf313f39bf5fbefc,0x3e16bf7d3f7f3d97,0x3f653ee6bf7abe60,0x3f5cbf043f133f51,0x3f7abe60bee6bf65,0x3f2cbf3e3f4a3f1d,0xbefcbf5fbf31bf39,
0x3f803d493cc93f80,0xbf6fbeb83dfbbf7e,0x3f78be793ea13f73,0xbd973f7fbe2fbf7c,0x3f4e3f18bf093f58,0x3f133f513f27bf42,0x3f713eacbe893f77,0x3f1dbf4a3ecfbf6a,
0x3f71beac3ee63f65,0xbd97bf7fbe60bf7a,0x3f7d3e16bcc93f80,0x3f6a3ecf3e89bf77,0x3e79bf783f7e3dfb,0x3f5f3efcbf6fbeb8,0x3f2cbf3e3f513f13,0xbf583f09bf27bf42,
0xbd493f80bf7f3d97,0x3f733ea13f7c3e2f,0xbf043f5cbf6abecf,0xbf393f313f4a3f1d,0x3f4e3f18befc3f5f,0xbf4a3f1d3f31bf39,0x3edb3f67bf583f09,0xbe2fbf7c3f73bea1,
0x3f2c3f3ebf1d3f4a,0x3efc3f5f3f58bf09,0x3f7d3e163cc93f80,0x3eb8bf6f3ea1bf73,0x3f5cbf043f273f42,0xbf733ea1beb8bf6f,0x3eacbf713f7c3e2f,0x3f583f09bf5fbefc,
0xbf67bedb3e89bf77,0xbf4abf1dbf133f51,0xbf783e79becfbf6a,0x3cc93f803d973f7f,0xbf183f4ebf65bee6,0x3f42bf273f313f39,0x3d493f80bf7a3e60,0xbf7cbe2f3f7e3dfb,
0xbf3e3f2cbf51bf13,0xbf09bf583efc3f5f,0xbf7dbe16bd97bf7f,0x3f733ea1beb83f6f,0xbf04bf5c3f39bf31,0xbf6f3eb8bf733ea1,0x3eacbf713f7e3dfb,0x3efcbf5fbf58bf09,
0x3edbbf673f7a3e60,0x3f513f13bf4abf1d,0x3f78be793ee63f65,0xbf7f3d97bcc9bf80,0x3f4e3f18becf3f6a,0x3f39bf313f42bf27,0x3d493f80bf773e89,0xbdfb3f7e3f7c3e2f,
0xbeacbf713f51bf13,0x3e603f7abf7f3d97,0xbf7dbe16bdfbbf7e,0x3e89bf77becf3f6a,0x3f783e793cc93f80,0x3f6f3eb83efcbf5f,0x3f2cbf3e3f653ee6,0xbf27bf42bf09bf58,
0x3f803d493e603f7a,0xbf7cbe2f3ea1bf73,0x3f04bf5c3f773e89,0x3f4a3f1dbf31bf39,0xbf183f4ebf6fbeb8,0xbf313f393f1d3f4a,0x3edb3f67bf423f27,0x3f73bea13f7cbe2f,
0x3f673edbbdfb3f7e,0x3efcbf5f3f31bf39,0xbe163f7dbf7c3e2f,0xbe603f7a3f653ee6,0xbf04bf5c3f27bf42,0x3f65bee6bf7a3e60,0x3f2cbf3e3f6a3ecf,0xbf393f31befcbf5f,
0xbd493f80bf773e89,0x3f7e3dfb3f6f3eb8,0xbf783e79bf09bf58,0xbf7c3e2fbd973f7f,0x3f18bf4e3f733ea1,0x3f423f27bf13bf51,0x3f713eacbcc93f80,0xbf6abecf3f1dbf4a,
0xbf80bd49bea1bf73,0xbf7fbd97becf3f6a,0xbe163f7dbf7a3e60,0x3f7c3e2f3f5f3efc,0x3f783e793dfb3f7e,0xbf77be893f13bf51,0x3eacbf713f80bcc9,0x3f6f3eb8bf42bf27,
0xbf67bedb3d97bf7f,0xbf65bee6bf393f31,0xbf043f5cbf7cbe2f,0x3f583f093f1d3f4a,0x3f4e3f18be893f77,0xbf4abf1d3f58bf09,0x3f2cbf3e3f6f3eb8,0x3f393f31bee6bf65,
0xbec4bf6d3f35bf35,0x3f8000003f353f35,0x3f6dbec43f353f35,0xbf800000bf35bf35,0x3ec43f6dbf353f35,0x3f8000003f353f35,0xbf6d3ec4bf35bf35,0xbf800000bf35bf35,
0xbec4bf6d3f35bf35,0x3f8000003f353f35,0x3f6dbec43f353f35,0xbf800000bf35bf35,0x3ec43f6dbf353f35,0x3f8000003f353f35,0xbf6d3ec4bf35bf35,0xbf800000bf35bf35,
0x3f80bd493ef13f62,0xbf75be95bf04bf5c,0xbe79bf783f46bf22,0x3f7f3dc93f2c3f3e,0xbf71beacbdc9bf7f,0xbf46bf22be16bf7d,0xbe163f7dbf753e95,0x3f623ef13eac3f71,
0x3f3e3f2cbe953f75,0xbef1bf623e79bf78,0x3f04bf5c3f7f3dc9,0x3f223f46bd493f80,0xbedbbf673f22bf46,0xbdc9bf7f3f18bf4e,0xbf4e3f18bf62bef1,0x3e953f75bedb3f67,
0xbf223f46bf7bbe48,0x3f0e3f55bdc93f7f,0xbef1bf623f0ebf55,0xbe48bf7b3ef1bf62,0xbdc9bf7f3f55bf0e,0x3f7b3e483f223f46,0x3f753e953e483f7b,0xbf55bf0ebe95bf75,
0xbf46bf223e48bf7b,0xbf553f0ebf7fbdc9,0x3f62bef13f553f0e,0x3f7bbe483f623ef1,0x3f7fbdc93f0e3f55,0xbe483f7bbf463f22,0xbe953f75bf7b3e48,0x3f0ebf553f75be95,
0x3e79bf783f75be95,0x3ef1bf623f67bedb,0xbf713eacbf46bf22,0x3dc93f7fbf043f5c,0x3f4e3f18bdc93f7f,0xbf22bf46bd49bf80,0x3d49bf803f62bef1,0x3f753e953f183f4e,
0x3f043f5cbef13f62,0x3e953f75beac3f71,0x3edbbf673f7fbdc9,0xbf46bf22be79bf78,0xbf7d3e16bf22bf46,0x3f7f3dc93f3e3f2c,0x3f2c3f3ebe953f75,0xbf623ef1bf7dbe16,
0xbe483f7bbf6d3ec4,0xbf6dbec4bf0ebf55,0xbf0ebf553ec4bf6d,0x3ec43f6dbe483f7b,0x3f7b3e483ec43f6d,0x3ec4bf6d3f55bf0e,0xbf553f0ebf6dbec4,0xbf6d3ec4bf7bbe48,
0x3e48bf7b3f6dbec4,0x3f6d3ec43f0e3f55,0x3f0e3f55bec43f6d,0xbec4bf6d3e48bf7b,0xbf7bbe48bec4bf6d,0xbec43f6dbf553f0e,0x3f55bf0e3f6d3ec4,0x3f6dbec43f7b3e48,
0x3f04bf5c3f7fbdc9,0xbf223f46bf713eac,0xbf673edbbf62bef1,0xbe95bf753e79bf78,0xbf18bf4e3e95bf75,0xbef1bf623d49bf80,0x3d493f80bf463f22,0x3f7f3dc93f4e3f18,
0x3e793f78bf223f46,0xbdc9bf7f3edbbf67,0x3eacbf713f75be95,0x3f623ef13f043f5c,0x3f7d3e163ef13f62,0x3f753e953f2c3f3e,0xbf3ebf2c3dc9bf7f,0xbf463f22bf7d3e16,
0xbf753e95bf55bf0e,0x3e483f7bbe953f75,0x3f46bf223f7b3e48,0x3f55bf0e3f7fbdc9,0xbf62bef1be48bf7b,0x3f0ebf553f62bef1,0x3f7f3dc93f0e3f55,0xbf7bbe48bf46bf22,
0xbe95bf753f0ebf55,0xbf7b3e48bf75be95,0x3f223f46be483f7b,0x3f0e3f553dc93f7f,0x3ef1bf623f7bbe48,0x3f553f0e3ef13f62,0xbdc93f7fbf553f0e,0x3e48bf7b3f22bf46,
0x3f2c3f3ebdc93f7f,0x3f223f463e793f78,0xbf04bf5c3e95bf75,0xbf623ef1bf803d49,0x3eac3f71bef13f62,0xbe95bf753e16bf7d,0xbe16bf7d3f22bf46,0x3f7fbdc93f713eac,
0xbd493f80bf463f22,0xbdc93f7fbf043f5c,0x3e79bf783f62bef1,0xbf75be95bf3ebf2c,0xbedb3f67bf753e95,0x3ef1bf623f4ebf18,0x3f18bf4e3f7fbdc9,0x3f463f223edb3f67,
0xbea1bf733f3ebf2c,0x3f803d493f313f39,0x3f7abe603f183f4e,0xbf7dbe16bf1dbf4a,0x3dfb3f7ebf5c3f04,0x3f783e793f093f58,0xbf803cc9bedbbf67,0xbf71beacbee6bf65,
0x3d97bf7f3f71beac,0x3f673edb3eb83f6f,0x3f7c3e2f3e793f78,0xbf5cbf04be89bf77,0xbe893f77bf7d3e16,0x3f4e3f183e2f3f7c,0xbf6fbeb8bd49bf80,0xbf3ebf2cbd97bf7f,
0x3f7e3dfb3eac3f71,0xbf67bedbbecfbf6a,0xbe2fbf7c3f4ebf18,0x3f7d3e163f273f42,0xbf42bf273e79bf78,0xbf04bf5c3e2fbf7c,0xbecf3f6abf803d49,0x3f3e3f2c3dfb3f7e,
0x3e893f77bf3e3f2c,0x3d49bf803f31bf39,0x3f58bf093f5c3f04,0x3e793f78bee63f65,0x3ea1bf733f7dbe16,0x3f18bf4e3f7abe60,0xbf80bcc9bedbbf67,0xbeac3f71bf5f3efc,
0xbf513f13bf67bedb,0x3eac3f71bea13f73,0xbdfbbf7e3f4ebf18,0x3e16bf7d3f39bf31,0xbcc9bf803f5cbf04,0x3f783e793f1d3f4a,0x3f653ee63d493f80,0xbf3ebf2cbe2fbf7c,
0xbe60bf7a3f3ebf2c,0xbf80bd49bf42bf27,0x3f773e893e793f78,0x3f5c3f043eb83f6f,0x3f6f3eb83e163f7d,0xbf183f4ebf773e89,0xbf423f27bf71beac,0x3f67bedb3f7a3e60,
0x3f13bf513f803d49,0x3f3ebf2c3f7ebdfb,0xbf7f3d97bf18bf4e,0xbe163f7dbf313f39,0x3f313f39be793f78,0xbf04bf5c3d97bf7f,0x3dfbbf7e3f67bedb,0x3f713eac3f133f51,
0xbe603f7abf713eac,0xbedb3f67bf5f3efc,0x3f65bee63f5c3f04,0xbe79bf783eb8bf6f,0xbf6abecfbe16bf7d,0x3f4e3f183ea13f73,0x3e893f77bf2c3f3e,0xbf803d49bf58bf09,
0xbf1d3f4abf80bd49,0xbf2cbf3ebe2fbf7c,0xbcc9bf803f4ebf18,0xbe163f7dbf273f42,0x3f273f42be793f78,0x3f5cbf043f803cc9,0xbf7cbe2fbedbbf67,0xbf71beacbf1dbf4a,
0x3e89bf773f71beac,0x3f673edb3f093f58,0x3ecf3f6abf043f5c,0xbe79bf783ea1bf73,0xbf65bee6be16bf7d,0xbf183f4ebf6f3eb8,0x3f7abe603f3e3f2c,0x3f80bd493f5f3efc,
0x3f65bee63f673edb,0xbf713eacbf7cbe2f,0xbf80bcc9bf18bf4e,0x3e16bf7d3f1dbf4a,0x3dfbbf7e3f5cbf04,0x3e79bf783f31bf39,0xbf133f51bf803d49,0x3f3e3f2c3ea13f73,
0x3d973f7fbf3e3f2c,0x3d49bf803f09bf58,0x3ecfbf6a3f78be79,0x3f5c3f043efc3f5f,0x3f5f3efc3e163f7d,0x3f4e3f183ecf3f6a,0xbf09bf583eacbf71,0xbf673edbbf7fbd97,
0xbf6fbeb8beacbf71,0xbedb3f67bf4a3f1d,0x3f7f3d973f183f4e,0x3f7d3e163f513f13,0xbf13bf513e79bf78,0x3f5cbf043f7fbd97,0x3f4a3f1d3d493f80,0xbf3ebf2cbeb8bf6f,
0xbcc9bf803f3ebf2c,0xbf80bd49bf5fbefc,0x3ea13f73bf043f5c,0x3e793f78be603f7a,0x3f09bf583f7dbe16,0x3f4e3f183ee63f65,0xbe893f77bf673edb,0x3eacbf713f39bf31,
0xbcc93f80bf3e3f2c,0xbd493f80bee63f65,0x3dfbbf7e3f4ebf18,0xbf7dbe16bf58bf09,0xbe603f7abf5c3f04,0x3e79bf783f1dbf4a,0x3ea1bf733f67bedb,0x3f713eac3f393f31,
0xbecf3f6abf713eac,0xbedb3f67bf423f27,0x3efcbf5f3f78be79,0xbf5cbf04bf13bf51,0xbf133f51bf7d3e16,0x3f18bf4e3f5fbefc,0x3f27bf423f80bd49,0x3f3e3f2c3ecf3f6a,
0x3ec43f6d3f35bf35,0x3f6d3ec43f353f35,0x3f6dbec4bf353f35,0x3ec4bf6d3f35bf35,0xbec4bf6d3f35bf35,0xbf6dbec4bf35bf35,0xbf6d3ec4bf353f35,0xbec43f6dbf353f35,
0x3ec43f6d3f35bf35,0x3f6d3ec43f353f35,0x3f6dbec4bf353f35,0x3ec4bf6d3f35bf35,0xbec4bf6d3f35bf35,0xbf6dbec4bf35bf35,0xbf6d3ec4bf353f35,0xbec43f6dbf353f35,
0x3f7dbe16bf673edb,0x3f2cbf3e3f62bef1,0x3eac3f713f4ebf18,0x3f5c3f043f223f46,0xbf78be79bf803d49,0xbf673edbbf7f3dc9,0x3d49bf803f78be79,0xbf18bf4ebe95bf75,
0x3f4e3f18bf71beac,0x3f80bd493f753e95,0xbedb3f673f7d3e16,0x3e793f78bdc93f7f,0xbf04bf5cbf3ebf2c,0xbf71beacbf46bf22,0x3f3ebf2c3f5c3f04,0x3e16bf7d3ef1bf62,
0x3ef1bf623f753e95,0xbdc9bf7f3e48bf7b,0xbf22bf46bf46bf22,0xbf75be95bf55bf0e,0x3e953f753f62bef1,0x3f463f223f0e3f55,0x3f7f3dc9bf7f3dc9,0x3f62bef13f7bbe48,
0x3f623ef1be953f75,0x3f7fbdc93f7b3e48,0x3f46bf223f22bf46,0x3e95bf753f0ebf55,0xbf753e953ef13f62,0xbf223f46bf553f0e,0xbdc93f7fbdc9bf7f,0x3ef13f623e483f7b,
0xbd49bf80be16bf7d,0xbf04bf5cbe95bf75,0x3f4ebf183f2c3f3e,0x3edbbf673f22bf46,0x3f713eacbf78be79,0x3f7dbe163f7f3dc9,0x3e793f783f71beac,0x3f2c3f3e3ef13f62,
0x3f3e3f2c3f4e3f18,0x3f783e793f623ef1,0xbe163f7dbf80bd49,0x3eac3f713dc93f7f,0xbf673edb3f5cbf04,0xbf183f4ebf463f22,0xbf5cbf04bedb3f67,0xbf80bd49bf75be95,
0xbe48bf7bbf7b3e48,0xbf0ebf55bec4bf6d,0xbf55bf0e3f553f0e,0xbf7bbe48bf6dbec4,0xbf7b3e48be48bf7b,0xbf553f0ebf6d3ec4,0xbf0e3f55bf0e3f55,0xbe483f7bbec43f6d,
0x3e483f7b3f7bbe48,0x3f0e3f553ec43f6d,0x3f553f0ebf55bf0e,0x3f7b3e483f6d3ec4,0x3f7bbe483e483f7b,0x3f55bf0e3f6dbec4,0x3f0ebf553f0ebf55,0x3e48bf7b3ec4bf6d,
0x3d49bf80be163f7d,0xbe79bf78bdc9bf7f,0x3f18bf4ebf3ebf2c,0x3eacbf713ef1bf62,0xbf67bedbbf5cbf04,0xbf7dbe16bf75be95,0xbf04bf5c3f67bedb,0xbf3ebf2cbf22bf46,
0x3f2c3f3ebf18bf4e,0x3f5c3f043f463f22,0x3e163f7d3f80bd49,0x3edb3f673e953f75,0x3f71beac3f78be79,0x3f4ebf183f62bef1,0x3f783e79beac3f71,0x3f80bd493f7f3dc9,
0x3f22bf463f223f46,0x3ef1bf623f0ebf55,0x3e95bf753ef1bf62,0x3dc9bf7f3e48bf7b,0x3f7fbdc93dc9bf7f,0x3f75be953f7bbe48,0x3f62bef1bf753e95,0x3f46bf223f55bf0e,
0x3f463f22bf463f22,0x3f623ef13f553f0e,0x3f753e953f623ef1,0x3f7f3dc93f7b3e48,0x3dc93f7f3f7f3dc9,0x3e953f753e483f7b,0x3ef13f62be95bf75,0x3f223f463f0e3f55,
0x3f7d3e163f673edb,0x3f803d493f7f3dc9,0x3f713eacbf183f4e,0x3f783e793f753e95,0x3f5c3f04bf2cbf3e,0x3f673edb3f623ef1,0x3f3e3f2c3f5cbf04,0x3f4e3f183f463f22,
0x3f183f4e3eac3f71,0x3f2c3f3e3f223f46,0x3edb3f67bf7d3e16,0x3f043f5c3ef13f62,0x3e793f783d49bf80,0x3eac3f713e953f75,0x3d493f803f783e79,0x3e163f7d3dc93f7f,
0x3eb83f6f3f42bf27,0x3f653ee63f2c3f3e,0x3f77be89bf513f13,0x3f09bf583f4ebf18,0xbe2fbf7c3f5fbefc,0xbf4abf1dbf04bf5c,0xbf7f3d97bf6a3ecf,0xbf313f39bf673edb,
0xbcc93f803f73bea1,0x3f273f423eac3f71,0x3f7e3dfbbf7a3e60,0x3f51bf133f78be79,0x3e60bf7a3f7ebdfb,0xbefcbf5fbe16bf7d,0xbf73bea1bf803cc9,0xbf6a3ecfbf803d49,
0x3f80bcc9bf773e89,0x3f4abf1d3f71beac,0x3ea13f733f58bf09,0x3f513f133f183f4e,0xbf58bf09bf73bea1,0xbf7f3d97bf78be79,0x3e89bf773f803cc9,0xbeb8bf6fbd49bf80,
0x3ecf3f6abf1dbf4a,0x3f5f3efc3f2c3f3e,0xbf423f273f513f13,0xbe603f7abf043f5c,0x3e2fbf7cbd97bf7f,0xbee6bf65be16bf7d,0x3f7ebdfb3eb83f6f,0x3f39bf313f67bedb,
0x3f27bf423f583f09,0x3e2fbf7c3edbbf67,0xbeb8bf6fbefcbf5f,0xbf4abf1dbf18bf4e,0x3e893f773f6abecf,0x3f393f313f043f5c,0x3f7a3e60bf7fbd97,0x3f73bea13f80bd49,
0x3ee63f65bf513f13,0x3f583f093f2c3f3e,0x3f803cc93f7ebdfb,0x3f5fbefc3f78be79,0xbf7ebdfb3cc93f80,0xbf6a3ecfbf7d3e16,0xbf133f513ee6bf65,0xbd973f7fbeac3f71,
0x3e89bf773e60bf7a,0xbe2fbf7c3d49bf80,0x3f6abecf3ee63f65,0x3f27bf423f4ebf18,0x3f653ee6bf6abecf,0x3f803cc93f783e79,0x3e603f7a3f77be89,0x3f1d3f4a3edb3f67,
0x3dfb3f7e3e2f3f7c,0x3f093f583eac3f71,0xbf313f39bf42bf27,0xbea13f73bf043f5c,0xbf7fbd973f803cc9,0xbf6f3eb8bf7d3e16,0xbf13bf51bf4a3f1d,0xbf5fbefcbf3ebf2c,
0x3e60bf7abf77be89,0xbdfbbf7e3d49bf80,0xbee6bf653ecf3f6a,0xbf39bf31bf18bf4e,0xbf6abecf3ee6bf65,0xbf7fbd97bf78be79,0xbf773e89bf7a3e60,0xbf513f13bf673edb,
0x3e2f3f7c3f7ebdfb,0x3efc3f5f3eac3f71,0x3f423f27bf39bf31,0x3f6f3eb83f5c3f04,0x3f803cc9bd973f7f,0x3f73bea13f7dbe16,0x3f4abf1d3f51bf13,0x3f09bf583f2cbf3e,
0x3f09bf58bf273f42,0x3ea1bf733edbbf67,0x3f5fbefcbeb8bf6f,0x3f39bf313f4ebf18,0xbecfbf6abe89bf77,0xbf1dbf4abf04bf5c,0x3d97bf7f3f7a3e60,0xbe2fbf7cbd49bf80,
0x3f133f51bee6bf65,0x3f423f273f2c3f3e,0x3dfb3f7e3f803cc9,0x3eb83f6f3e793f78,0x3f80bcc93f7e3dfb,0x3f77be893f7dbe16,0x3f653ee6bf133f51,0x3f7a3e603f713eac,
0x3f77be893cc93f80,0x3f6abecf3f71beac,0x3f58bf093f73bea1,0x3f42bf273f4ebf18,0x3f733ea13f09bf58,0x3f7c3e2f3f783e79,0x3f803cc9bf77be89,0x3f7ebdfb3f80bd49,
0x3f1d3f4abf6a3ecf,0x3f393f313f2c3f3e,0x3f513f133f273f42,0x3f653ee63f5c3f04,0x3d973f7f3f7c3e2f,0x3e603f7a3e163f7d,0x3eb83f6fbdfbbf7e,0x3efc3f5f3edb3f67,
0x3f273f423eb83f6f,0x3f313f393f2c3f3e,0x3f133f51bf773e89,0x3f1d3f4a3f183f4e,0x3efc3f5fbe2fbf7c,0x3f093f583f043f5c,0x3ecf3f6a3f7fbd97,0x3ee63f653edb3f67,
0x3ea13f73bcc93f80,0x3eb83f6f3eac3f71,0x3e603f7abf7ebdfb,0x3e893f773e793f78,0x3dfb3f7e3e60bf7a,0x3e2f3f7c3e163f7d,0x3cc93f803f733ea1,0x3d973f7f3d493f80,
};
__device__ __align__(1024) uint8_t g_hT[32 * 262144];
__device__ __align__(1024) bf16 g_U[128 * 2 * 8 * 1024];
__device__ __align__(128) float g_gp[128 * 256];
__device__ __align__(128) uint4 g_agg[16 * 512];
#define CS 32
__device__ __align__(128) unsigned g_cnt[8 * 32];
constexpr int CNT_U = 0, CNT_V = 1, CNT_H = 2  , CNT_DONE = 4, CNT_EPOCH = 5;
#define PROFK(i) do { } while (0)
#define PROFC(i) do { } while (0)
#define PROF(i) do { } while (0)
#define PROFX(i) do { } while (0)
#define PROFS(i) do { } while (0)
#define PROFG(i) do { } while (0)

constexpr int SLOT = 32768;
constexpr int OFF_HS = 4 * SLOT;
constexpr int OFF_W = OFF_HS + 16384;
constexpr int OFF_F = OFF_W + 2 * 18432;
constexpr int OFF_G = OFF_F + 8192;
constexpr int OFF_K = OFF_G + 1024;
constexpr int OFF_GW = OFF_K + 2048;
constexpr int OFF_U = 6 * SLOT;
constexpr int OFF_BAR = OFF_U + 32768;
constexpr int OFF_SC = OFF_BAR + 320;
constexpr int OFF_KEPT = OFF_SC + 1024;
constexpr int OFF_PROF = OFF_KEPT + 64;
constexpr int SMEM_BYTES = OFF_PROF;
constexpr int BAR_FULL = 0  , BAR_X = 10, BAR_U = 11, BAR_W = 12  , BAR_F = 14  ,
              BAR_EMPTY = 17  , BAR_HW = 22  , BAR_WR = 25, BAR_VW = 26, BAR_S1 = 27,
              BAR_XC = 28  , BAR_HR = 32,
              BAR_CD = 33, BAR_C = 34  , BAR_HD = 36  ;

#define DEVI __device__ __forceinline__
constexpr unsigned SPIN_LIMIT = 1u << 22;

DEVI uint32_t smem_u32(const void* p) { return (uint32_t)__cvta_generic_to_shared(p); }
DEVI uint64_t gtime() { uint64_t t; asm volatile("mov.u64 %0, %%globaltimer;" : "=l"(t)); return t; }
DEVI void mbar_init(uint32_t bar, uint32_t cnt) { asm volatile("mbarrier.init.shared::cta.b64 [%0], %1;" :: "r"(bar), "r"(cnt) : "memory"); }
DEVI void mbar_expect_tx(uint32_t bar, uint32_t bytes) { asm volatile("mbarrier.arrive.expect_tx.shared::cta.b64 _, [%0], %1;" :: "r"(bar), "r"(bytes) : "memory"); }
DEVI void mbar_arrive(uint32_t bar) { asm volatile("mbarrier.arrive.shared::cta.b64 _, [%0];" :: "r"(bar) : "memory"); }
DEVI void mbar_wait(uint32_t bar, uint32_t parity) {
    asm volatile("{\n.reg .pred p;\n.reg .u32 n;\nmov.u32 n, 0;\n"
                 "LW:\nmbarrier.try_wait.parity.shared::cta.b64 p, [%0], %1;\n@p bra LD;\n"
                 "add.u32 n, n, 1;\nsetp.lt.u32 p, n, %2;\n@p bra LW;\nLD:\n}"
                 :: "r"(bar), "r"(parity), "n"(1 << 17) : "memory");
}
DEVI bool elect() {
    uint32_t p;
    asm volatile("{\n.reg .pred P;\nelect.sync _|P, 0xffffffff;\nselp.u32 %0, 1, 0, P;\n}" : "=r"(p));
    return p;
}
DEVI void fence_barrier_init() { asm volatile("fence.mbarrier_init.release.cluster;" ::: "memory"); }
DEVI void fence_proxy_async_smem() { asm volatile("fence.proxy.async.shared::cta;" ::: "memory"); }
DEVI void helper_sync() { asm volatile("bar.sync 1, 128;" ::: "memory"); }

DEVI void pause(unsigned n) {
    asm volatile("{\n.reg .pred p;\n.reg .u32 a, b;\nmov.u32 a, %%clock;\n"
                 "LP:\nmov.u32 b, %%clock;\nsub.u32 b, b, a;\nsetp.lt.u32 p, b, %0;\n@p bra LP;\n}" :: "r"(n) : "memory");
}
DEVI void sched_fence() { asm volatile("{\n.reg .pred p;\n.reg .b32 n;\nLP:\nactivemask.b32 n;\nsetp.eq.u32 p, n, 0;\n@p bra LP;\n}" ::: "memory"); }
#define P_POLL 0
#define NPOLL 1
DEVI void wait_counter(const unsigned* p, unsigned target) {
    unsigned v[NPOLL];
    auto ld = [&](int i) { asm volatile("ld.relaxed.gpu.global.u32 %0, [%1];" : "=r"(v[i]) : "l"(p) : "memory"); };
#pragma unroll
    for (int i = 0; i < NPOLL; i++) { if (i) pause(200); ld(i); }
#pragma unroll 1
    for (unsigned n = 0; n < SPIN_LIMIT; n++) {
#pragma unroll
        for (int i = 0; i < NPOLL; i++) {
            if ((int)(v[i] - target) >= 0) return;
            if (P_POLL) pause(P_POLL);
            ld(i);
        }
    }
}
DEVI void signal_counter(unsigned* p) {
    asm volatile("red.relaxed.gpu.global.add.u32 [%0], 1;" :: "l"(p) : "memory");
}

DEVI void tma_load_3d(uint32_t dst, const CUtensorMap* map, uint32_t bar, int c0, int c1, int c2) {
    asm volatile("cp.async.bulk.tensor.3d.shared::cluster.global.mbarrier::complete_tx::bytes [%0], [%1, {%3, %4, %5}], [%2];"
        :: "r"(dst), "l"(map), "r"(bar), "r"(c0), "r"(c1), "r"(c2) : "memory");
}
DEVI void tma_load_4d(uint32_t dst, const CUtensorMap* map, uint32_t bar, int c0, int c1, int c2, int c3) {
    asm volatile("cp.async.bulk.tensor.4d.shared::cluster.global.mbarrier::complete_tx::bytes [%0], [%1, {%3, %4, %5, %6}], [%2];"
        :: "r"(dst), "l"(map), "r"(bar), "r"(c0), "r"(c1), "r"(c2), "r"(c3) : "memory");
}
DEVI void tma_load_5d(uint32_t dst, const CUtensorMap* map, uint32_t bar, int c0, int c3, int c4) {
    asm volatile("cp.async.bulk.tensor.5d.shared::cluster.global.mbarrier::complete_tx::bytes [%0], [%1, {%3, %6, %6, %4, %5}], [%2];"
        :: "r"(dst), "l"(map), "r"(bar), "r"(c0), "r"(c3), "r"(c4), "r"(0) : "memory");
}
DEVI void tma_store_4d(const CUtensorMap* map, uint32_t src, int c0, int c1, int c2, int c3) {
    asm volatile("cp.async.bulk.tensor.4d.global.shared::cta.bulk_group [%0, {%2, %3, %4, %5}], [%1];"
        :: "l"(map), "r"(src), "r"(c0), "r"(c1), "r"(c2), "r"(c3) : "memory");
}
DEVI void bulk_load(uint32_t dst, const void* src, uint32_t bytes, uint32_t bar) {
    asm volatile("cp.async.bulk.shared::cluster.global.mbarrier::complete_tx::bytes [%0], [%1], %2, [%3];"
        :: "r"(dst), "l"(src), "r"(bytes), "r"(bar) : "memory");
}
DEVI void bulk_prefetch_l2(const void* src, uint32_t bytes) {
    asm volatile("cp.async.bulk.prefetch.L2.global [%0], %1;" :: "l"(src), "r"(bytes) : "memory");
}
DEVI void tma_store_3d(const CUtensorMap* map, uint32_t src, int c0, int c1, int c2) {
    asm volatile("cp.async.bulk.tensor.3d.global.shared::cta.bulk_group [%0, {%2, %3, %4}], [%1];"
        :: "l"(map), "r"(src), "r"(c0), "r"(c1), "r"(c2) : "memory");
}
DEVI void bulk_store(void* dst, uint32_t src, uint32_t bytes) {
    asm volatile("cp.async.bulk.global.shared::cta.bulk_group [%0], [%1], %2;" :: "l"(dst), "r"(src), "r"(bytes) : "memory");
}
DEVI void bulk_commit() { asm volatile("cp.async.bulk.commit_group;" ::: "memory"); }
DEVI void bulk_wait0() { asm volatile("cp.async.bulk.wait_group 0;" ::: "memory"); }

DEVI void wgmma_fence() { asm volatile("wgmma.fence.sync.aligned;" ::: "memory"); }
DEVI void wgmma_commit() { asm volatile("wgmma.commit_group.sync.aligned;" ::: "memory"); }
template<int N> DEVI void wgmma_wait() { asm volatile("wgmma.wait_group.sync.aligned %0;" :: "n"(N) : "memory"); }
template<int N> DEVI void wgmma_wait_all(float (&d)[N]) {
    wgmma_wait<0>();
#pragma unroll
    for (int i = 0; i < N; i++) asm volatile("" : "+f"(d[i]) :: "memory");
}
template<int R> DEVI void reg_alloc() { asm volatile("setmaxnreg.inc.sync.aligned.u32 %0;" :: "n"(R)); }
template<int R> DEVI void reg_dealloc() { asm volatile("setmaxnreg.dec.sync.aligned.u32 %0;" :: "n"(R)); }

DEVI uint64_t make_desc(uint32_t addr, uint32_t lbo, uint32_t sbo, uint32_t mode = 1) {
    return (uint64_t)(((addr & 0x3FFFF) >> 4) | ((lbo >> 4) << 16)) | ((uint64_t)((sbo >> 4) | (mode << 30)) << 32);
}

#define ACC8(a, o) "+f"(a[o+0]), "+f"(a[o+1]), "+f"(a[o+2]), "+f"(a[o+3]), "+f"(a[o+4]), "+f"(a[o+5]), "+f"(a[o+6]), "+f"(a[o+7])
#define OUT8(a, o) "=f"(a[o+0]), "=f"(a[o+1]), "=f"(a[o+2]), "=f"(a[o+3]), "=f"(a[o+4]), "=f"(a[o+5]), "=f"(a[o+6]), "=f"(a[o+7])
#define ACC32(a, o) ACC8(a, o), ACC8(a, o+8), ACC8(a, o+16), ACC8(a, o+24)

template<int TA, int TB>
DEVI void wgmma_n128(float (&d)[64], uint64_t da, uint64_t db, int scale_d) {
    asm volatile("{\n.reg .pred p;\nsetp.ne.b32 p, %66, 0;\n"
        "wgmma.mma_async.sync.aligned.m64n128k16.f32.bf16.bf16 "
        "{%0, %1, %2, %3, %4, %5, %6, %7, %8, %9, %10, %11, %12, %13, %14, %15, "
        "%16, %17, %18, %19, %20, %21, %22, %23, %24, %25, %26, %27, %28, %29, %30, %31, "
        "%32, %33, %34, %35, %36, %37, %38, %39, %40, %41, %42, %43, %44, %45, %46, %47, "
        "%48, %49, %50, %51, %52, %53, %54, %55, %56, %57, %58, %59, %60, %61, %62, %63}, "
        "%64, %65, p, 1, 1, %67, %68;\n}\n"
        : ACC32(d, 0), ACC32(d, 32)
        : "l"(da), "l"(db), "r"(scale_d), "n"(TA), "n"(TB));
}
#define SS_N16 "{\n.reg .pred p;\nsetp.ne.b32 p, 0, 0;\n" \
        "wgmma.mma_async.sync.aligned.m64n16k16.f32.bf16.bf16 " \
        "{%0, %1, %2, %3, %4, %5, %6, %7}, %8, %9, p, 1, 1, %10, 0;\n}\n"
template<int TA> DEVI void wgmma_n16(float* d, uint64_t da, uint64_t db) {
    asm volatile(SS_N16 : OUT8(d, 0) : "l"(da), "l"(db), "n"(TA));
}
#define SS_N8 "{\n.reg .pred p;\nsetp.ne.b32 p, %6, 0;\n" \
        "wgmma.mma_async.sync.aligned.m64n8k16.f32.bf16.bf16 {%0, %1, %2, %3}, %4, %5, p, 1, 1, 0, 0;\n}\n"
DEVI void wgmma_n8(float (&d)[4], uint64_t da, uint64_t db, bool add) {
    if (add) asm volatile(SS_N8 : "+f"(d[0]), "+f"(d[1]), "+f"(d[2]), "+f"(d[3]) : "l"(da), "l"(db), "n"(1));
    else asm volatile(SS_N8 : "=f"(d[0]), "=f"(d[1]), "=f"(d[2]), "=f"(d[3]) : "l"(da), "l"(db), "n"(0));
}
#define RS_N64 "{\n.reg .pred p;\nsetp.ne.b32 p, %37, 0;\n" \
        "wgmma.mma_async.sync.aligned.m64n64k16.f32.bf16.bf16 " \
        "{%0, %1, %2, %3, %4, %5, %6, %7, %8, %9, %10, %11, %12, %13, %14, %15, " \
        "%16, %17, %18, %19, %20, %21, %22, %23, %24, %25, %26, %27, %28, %29, %30, %31}, " \
        "{%32, %33, %34, %35}, %36, p, 1, 1, %38;\n}\n"
template<int SCALE_D, int TB = 0>
DEVI void wgmma_rs_n64(float (&d)[32], const uint32_t (&a)[4], uint64_t db) {
    if (SCALE_D) asm volatile(RS_N64 : ACC32(d, 0) : "r"(a[0]), "r"(a[1]), "r"(a[2]), "r"(a[3]), "l"(db), "n"(1), "n"(TB));
    else asm volatile(RS_N64 : OUT8(d, 0), OUT8(d, 8), OUT8(d, 16), OUT8(d, 24) : "r"(a[0]), "r"(a[1]), "r"(a[2]), "r"(a[3]), "l"(db), "n"(0), "n"(TB));
}
#define SS_N64 "{\n.reg .pred p;\nsetp.ne.b32 p, %34, 0;\n" \
        "wgmma.mma_async.sync.aligned.m64n64k16.f32.bf16.bf16 " \
        "{%0, %1, %2, %3, %4, %5, %6, %7, %8, %9, %10, %11, %12, %13, %14, %15, " \
        "%16, %17, %18, %19, %20, %21, %22, %23, %24, %25, %26, %27, %28, %29, %30, %31}, " \
        "%32, %33, p, 1, 1, 0, 1;\n}\n"
template<int SCALE_D> DEVI void wgmma_ss_n64(float (&d)[32], uint64_t da, uint64_t db) {
    if (SCALE_D) asm volatile(SS_N64 : ACC32(d, 0) : "l"(da), "l"(db), "n"(1));
    else asm volatile(SS_N64 : OUT8(d, 0), OUT8(d, 8), OUT8(d, 16), OUT8(d, 24) : "l"(da), "l"(db), "n"(0));
}
DEVI void ldsm_x4_t(uint32_t (&r)[4], uint32_t addr) {
    asm volatile("ldmatrix.sync.aligned.m8n8.x4.trans.shared.b16 {%0, %1, %2, %3}, [%4];"
        : "=r"(r[0]), "=r"(r[1]), "=r"(r[2]), "=r"(r[3]) : "r"(addr) : "memory");
}
DEVI void ldsm_x4(uint32_t (&r)[4], uint32_t addr) {
    asm volatile("ldmatrix.sync.aligned.m8n8.x4.shared.b16 {%0, %1, %2, %3}, [%4];"
        : "=r"(r[0]), "=r"(r[1]), "=r"(r[2]), "=r"(r[3]) : "r"(addr) : "memory");
}
DEVI void stsm_x4(uint32_t addr, uint32_t r0, uint32_t r1, uint32_t r2, uint32_t r3) {
    asm volatile("stmatrix.sync.aligned.m8n8.x4.shared.b16 [%0], {%1, %2, %3, %4};"
        :: "r"(addr), "r"(r0), "r"(r1), "r"(r2), "r"(r3) : "memory");
}
DEVI void stsm_x4_t(uint32_t addr, uint32_t r0, uint32_t r1, uint32_t r2, uint32_t r3) {
    asm volatile("stmatrix.sync.aligned.m8n8.x4.trans.shared.b16 [%0], {%1, %2, %3, %4};"
        :: "r"(addr), "r"(r0), "r"(r1), "r"(r2), "r"(r3) : "memory");
}
DEVI uint32_t movm(uint32_t a) { uint32_t d; asm volatile("movmatrix.sync.aligned.m8n8.trans.b16 %0, %1;" : "=r"(d) : "r"(a)); return d; }
DEVI uint32_t pack2(float lo, float hi) { uint32_t d; asm("cvt.rn.bf16x2.f32 %0, %1, %2;" : "=r"(d) : "f"(hi), "f"(lo)); return d; }
DEVI float bf_lo(uint32_t v) { return __uint_as_float(v << 16); }
DEVI float bf_hi(uint32_t v) { return __uint_as_float(v & 0xffff0000u); }
DEVI float bf_round(float v) { return __bfloat162float(__float2bfloat16_rn(v)); }
DEVI uint32_t bf_mul2(uint32_t a, uint32_t b) { uint32_t d; asm("mul.rn.bf16x2 %0, %1, %2;" : "=r"(d) : "r"(a), "r"(b)); return d; }
DEVI uint32_t bf_add2(uint32_t a, uint32_t b) { uint32_t d; asm("add.rn.bf16x2 %0, %1, %2;" : "=r"(d) : "r"(a), "r"(b)); return d; }
DEVI uint32_t bf_sub2(uint32_t a, uint32_t b) { uint32_t d; asm("sub.rn.bf16x2 %0, %1, %2;" : "=r"(d) : "r"(a), "r"(b)); return d; }
DEVI uint4 lds128u(uint32_t a) { uint4 v; asm volatile("ld.shared.v4.u32 {%0, %1, %2, %3}, [%4];" : "=r"(v.x), "=r"(v.y), "=r"(v.z), "=r"(v.w) : "r"(a) : "memory"); return v; }
DEVI void sts128u(uint32_t a, uint32_t x, uint32_t y, uint32_t z, uint32_t w) { asm volatile("st.shared.v4.u32 [%0], {%1, %2, %3, %4};" :: "r"(a), "r"(x), "r"(y), "r"(z), "r"(w) : "memory"); }
DEVI uint2 lds64u(uint32_t a) { uint2 v; asm volatile("ld.shared.v2.u32 {%0, %1}, [%2];" : "=r"(v.x), "=r"(v.y) : "r"(a) : "memory"); return v; }
DEVI uint32_t ldg32u(const void* p) { uint32_t v; asm volatile("ld.global.nc.u32 %0, [%1];" : "=r"(v) : "l"(p) : "memory"); return v; }
DEVI void sts64(uint32_t a, float x, float y) { asm volatile("st.shared.v2.f32 [%0], {%1, %2};" :: "r"(a), "f"(x), "f"(y) : "memory"); }
DEVI void sts32(uint32_t a, uint32_t v) { asm volatile("st.shared.u32 [%0], %1;" :: "r"(a), "r"(v) : "memory"); }
DEVI uint32_t lds16(uint32_t a) { uint32_t v; asm volatile("ld.shared.u16 %0, [%1];" : "=r"(v) : "r"(a) : "memory"); return v; }
DEVI void cmul2(uint32_t& x, uint32_t& y, uint32_t c, uint32_t s, uint32_t n) {
    asm("{\n.reg .b32 t, u;\nmul.rn.bf16x2 t, %1, %4;\nmul.rn.bf16x2 u, %1, %2;\n"
        "fma.rn.bf16x2 %1, %0, %3, u;\nfma.rn.bf16x2 %0, %0, %2, t;\n}" : "+r"(x), "+r"(y) : "r"(c), "r"(s), "r"(n));
}
DEVI uint32_t neg2(uint32_t s) { uint32_t n; asm volatile("xor.b32 %0, %1, 0x80008000;" : "=r"(n) : "r"(s)); return n; }
DEVI void cmul2(uint32_t& x, uint32_t& y, uint32_t c, uint32_t s) { cmul2(x, y, c, s, neg2(s)); }
DEVI void cmul2c(uint32_t& x, uint32_t& y, uint32_t c, uint32_t s) { cmul2(x, y, c, neg2(s), s); }
DEVI void sts16(uint32_t a, float v) { asm volatile("st.shared.u16 [%0], %1;" :: "r"(a), "r"(pack2(v, v)) : "memory"); }

DEVI float2 cmul(float2 a, float2 b) { return make_float2(fmaf(a.x, b.x, -a.y * b.y), fmaf(a.x, b.y, a.y * b.x)); }
DEVI float2 cfma(float2 a, float2 b, float2 c) { return make_float2(fmaf(a.x, b.x, fmaf(-a.y, b.y, c.x)), fmaf(a.x, b.y, fmaf(a.y, b.x, c.y))); }

struct Params {
    const bf16 *lam_re, *lam_im, *log_dt, *dskip, *gate_w, *c_re, *c_im, *b_re, *b_im, *x;
    int swapB;
};

#define R8_POLL 8
#define R8B 1
#define SCB 32
#define C0 1
#define R8L 8
DEVI void radix8(uint32_t sb, bool inv, int w, int lane, int bar) {
    const uint64_t dg = make_desc(sb + OFF_G + (inv ? 512 : 0), 128, 256, 0), da = make_desc(sb + OFF_U, 16, 16384);
    float acc[2][64];
#pragma unroll
    for (int i = 0; i < 2; i++) {
        wgmma_fence();
#pragma unroll
        for (int j = 0; j < 8; j++) wgmma_n16<1>(acc[i] + 8 * j, da + 64 * (8 * i + j), dg);
        wgmma_commit();
    }
    const int kk = lane & 7, ch = 2 * w + ((lane >> 3) & 1);
    const uint32_t st = sb + OFF_U + (inv ? (lane >> 4) * 16384 + kk * 128 + ((ch ^ kk) << 4)
        : (kk & 1) * 16384 + (kk >> 2) * 2048 + (lane >> 4) * 1024 + (w >> 1) * 128 + ((((kk & 2) * 2 + ((ch & 3) ^ (kk >> 2) ^ (2 * (kk & 1)))) ^ (w >> 1)) << 4));
    uint32_t sa[4];
#pragma unroll
    for (int i = 0; i < 4; i++) sa[i] = inv ? (st ^ (i << 4)) + i * 1024 : (st ^ (i << 5)) + i * 256;
    uint32_t p[32];
#pragma unroll
    for (int i = 0; i < 2; i++) {
        if (i == 0) wgmma_wait<1>();
#pragma unroll
        for (int j = 0; j < 64; j++) asm volatile("" : "+f"(acc[i][j]) :: "memory");
#pragma unroll
        for (int j = 0; j < 32; j++) p[j] = pack2(acc[i][2 * j], acc[i][2 * j + 1]);
        if (i == 0) {
#pragma unroll
            for (int j = 0; j < 32; j++) asm volatile("" : "+r"(p[j]) :: "memory");
            wgmma_wait<0>();
            asm volatile("bar.sync %0, 128;" :: "r"(bar) : "memory");
        }
#pragma unroll
        for (int j = 0; j < 8; j++) stsm_x4_t(sa[j & 3] + (2 * i + (j >> 2)) * 4096, p[4 * j], p[4 * j + 1], p[4 * j + 2], p[4 * j + 3]);
    }
}

template<int N> DEVI void c_take(float (&acc)[32], uint32_t (&p)[16]) {
    wgmma_wait<N>();
#pragma unroll
    for (int i = 0; i < 32; i++) asm volatile("" : "+f"(acc[i]) :: "memory");
#pragma unroll
    for (int i = 0; i < 16; i++) p[i] = pack2(acc[2 * i], acc[2 * i + 1]);
}
DEVI void c_cols(float (&acc)[32], uint64_t df, uint64_t db) {
    wgmma_fence();
    wgmma_ss_n64<0>(acc, df, db);
#pragma unroll
    for (int s = 1; s < 4; s++) wgmma_ss_n64<1>(acc, df + 2 * s, db + 256 * s);
    wgmma_commit();
}

DEVI void phase_c(uint32_t sb, int ps, bool rot, int w, int lane, const uint4 (&tw)[4]) {
    const int warp = ps, bar = 5 + ps;
    PROFC(0);
    const uint32_t rb = sb + OFF_U + ps * 16384;
    const uint64_t df = make_desc(sb + OFF_F, 16, 1024), db = make_desc(rb, 16, 1024);
    float acc[2][32];
    c_cols(acc[0], df, db);
    c_cols(acc[1], df, db + 128);
    const int g = lane & 7, l3 = (lane >> 3) & 1, l4 = lane >> 4;
    uint32_t wf[2][4][4];
    const uint32_t wo = sb + OFF_W + (1 - ps) * 18432 + l4 * 9216 + g * 64 + ((w ^ (g >> 1)) << 4);
#pragma unroll
    for (int h = 0; h < 2; h++) {
        const uint32_t wm = wo + 4608 + (((rot ? 4 : 3) - 2 * h - l3) & 3) * 1152;
#pragma unroll
        for (int j = 0; j < 4; j++) ldsm_x4_t(wf[h][j], (j < 2 ? wo + (2 * h + l3) * 1152 : wm) + (j & 1) * 512);
    }
    uint32_t tn[8];
#pragma unroll
    for (int j = 0; j < 8; j++) tn[j] = neg2((j & 1) ? tw[j >> 1].w : tw[j >> 1].y);
    auto twiddle = [&](uint32_t& x, uint32_t& y, int j) { cmul2(x, y, (j & 1) ? tw[j >> 1].z : tw[j >> 1].x, (j & 1) ? tw[j >> 1].w : tw[j >> 1].y, tn[j]); };
#pragma unroll
    for (int h = 0; h < 2; h++) {
        uint32_t p[16], a[4][4];
        c_take<1>(acc[h], p);
        if (h == 0) PROFC(1);
#pragma unroll
        for (int i = 0; i < 8; i++) {
            twiddle(p[2 * i], p[2 * i + 1], (i & 3) ^ h);
            a[(i & 3) ^ h][i >> 2] = p[2 * i];
            a[(i & 3) ^ h][2 + (i >> 2)] = p[2 * i + 1];
        }
        wgmma_fence();
        wgmma_rs_n64<0>(acc[h], a[0], df + 4 * ps);
        wgmma_rs_n64<1>(acc[h], a[1], df + 4 * ps + 2);
        wgmma_rs_n64<1>(acc[h], a[2], df + 4 - 4 * ps);
        wgmma_rs_n64<1>(acc[h], a[3], df + 6 - 4 * ps);
        wgmma_commit();
    }
    PROFC(2);
#pragma unroll
    for (int h = 0; h < 2; h++) {
        uint32_t p[16], a[4][4];
        c_take<1>(acc[h], p);
#pragma unroll
        for (int i = 0; i < 8; i++) {
            const int j = i >> 1, r = i & 1;
            if (j < 2) cmul2(p[4 * j + r], p[4 * j + 2 + r], wf[h][j][r], wf[h][j][2 + r]);
            else cmul2c(p[4 * j + r], p[4 * j + 2 + r], wf[h][j][r], wf[h][j][2 + r]);
            a[j][r] = p[4 * j + 2 + r];
            a[j][2 + r] = p[4 * j + r];
        }
        wgmma_fence();
        wgmma_rs_n64<0>(acc[h], a[0], df);
#pragma unroll
        for (int j = 1; j < 4; j++) wgmma_rs_n64<1>(acc[h], a[j], df + 2 * j);
        wgmma_commit();
    }
    PROFC(3);
    const uint32_t xa = rb + w * 4096 + l4 * 1024 + g * 128 + (((4 * l3) ^ g) << 4);
#pragma unroll
    for (int h = 0; h < 2; h++) {
        uint32_t p[16];
        if (h) c_take<0>(acc[1], p); else c_take<1>(acc[0], p);
#pragma unroll
        for (int i = 0; i < 8; i++) twiddle(p[4 * (i >> 1) + (i & 1)], p[4 * (i >> 1) + 2 + (i & 1)], 4 + (i >> 1));
#pragma unroll
        for (int i = 0; i < 16; i++) asm volatile("" : "+r"(p[i]) :: "memory");
        if (h) fence_proxy_async_smem();
        asm volatile("bar.sync %0, 128;" :: "r"(bar) : "memory");
        if (h) c_cols(acc[0], df, db);
#pragma unroll
        for (int j = 0; j < 4; j++) stsm_x4((xa ^ (j << 4)) + h * 2048, p[4 * j], p[4 * j + 1], p[4 * j + 2], p[4 * j + 3]);
    }
    fence_proxy_async_smem();
    asm volatile("bar.sync %0, 128;" :: "r"(bar) : "memory");
    c_cols(acc[1], df, db + 128);
    PROFC(4);
    const uint32_t oa = rb + (4 * w + (g >> 1)) * 1024 + (1 - l3) * 512 + (((4 * (g & 1) + l4) ^ (4 - 4 * l3) ^ (g >> 1)) << 4);
#pragma unroll
    for (int h = 0; h < 2; h++) {
        uint32_t p[16];
        if (h) c_take<0>(acc[1], p);
        else {
            c_take<1>(acc[0], p);
#pragma unroll
            for (int i = 0; i < 16; i++) asm volatile("" : "+r"(p[i]) :: "memory");
            wgmma_wait<0>();
            asm volatile("bar.sync %0, 128;" :: "r"(bar) : "memory");
        }
#pragma unroll
        for (int i = 0; i < 4; i++) {
            const int r = 2 * h + (i >> 1);
            stsm_x4((oa ^ ((r ^ (2 * (i & 1))) << 4)) + r * 128, p[4 * i], p[4 * i + 1], p[4 * i + 2], p[4 * i + 3]);
        }
    }
    PROFC(5);
}

#define P_T 100
#define P_C 300
#define PACE_HA 200
#define PACE_HB 0
#define HN 4
#define PACE_V 100
#define VPOS 27
#define PACE_H 200
#define T_W0 2000
#define T_XS 2000
#define D_XS 0
#define P_XS 500
#define T_G 0
#define T_BA 1000
#define T_W1 3000
#define P_W 0
#define P_XE 600
#define P_R0 0
#define POL2 0
#define T_B2 4000
#define T_W 5000
#define PACE_U 200
#define PACE_L 0
#define T_FA 0
#define REG_M 216
#define REG_H 72
#define NS 4
#define SLOT_OF(k) (((k) + 1) % 4)
DEVI void tma_prefetch_4d(const CUtensorMap* map, int c0, int c1, int c2, int c3) {
    asm volatile("cp.async.bulk.prefetch.tensor.4d.L2.global [%0, {%1, %2, %3, %4}];" :: "l"(map), "r"(c0), "r"(c1), "r"(c2), "r"(c3) : "memory");
}
DEVI void bar_sync(int id, int n) { asm volatile("bar.sync %0, %1;" :: "r"(id), "r"(n) : "memory"); }
DEVI void bar_arrive(int id, int n) { asm volatile("bar.arrive %0, %1;" :: "r"(id), "r"(n) : "memory"); }
DEVI uint4 ldg128(const void* p) { uint4 v; asm volatile("ld.global.nc.v4.u32 {%0, %1, %2, %3}, [%4];" : "=r"(v.x), "=r"(v.y), "=r"(v.z), "=r"(v.w) : "l"(p)); return v; }
DEVI uint32_t ldg16(const void* p) { uint32_t v; asm volatile("ld.global.nc.u16 %0, [%1];" : "=r"(v) : "l"(p)); return v; }
DEVI uint32_t bf_fma2(uint32_t a, uint32_t b, uint32_t c) { uint32_t d; asm("fma.rn.bf16x2 %0, %1, %2, %3;" : "=r"(d) : "r"(a), "r"(b), "r"(c)); return d; }
DEVI void bulk_wait_read() { asm volatile("cp.async.bulk.wait_group.read 0;" ::: "memory"); }

DEVI float lds32f(uint32_t a) { float v; asm volatile("ld.shared.f32 %0, [%1];" : "=f"(v) : "r"(a) : "memory"); return v; }
DEVI uint32_t mbar_test(uint32_t bar, uint32_t parity) {
    uint32_t ok;
    asm volatile("{\n.reg .pred p;\nmbarrier.test_wait.parity.shared::cta.b64 p, [%1], %2;\nselp.u32 %0, 1, 0, p;\n}" : "=r"(ok) : "r"(bar), "r"(parity) : "memory");
    return ok;
}
template<int TA> DEVI void ring_steps(float (&acc)[2][64], uint32_t sb, uint32_t fb, int n, int ns, int& s, uint32_t& phm, bool first, bool lead, uint32_t rel, int first_bar, int last_bar, int pi) {
    const uint64_t da0 = TA ? make_desc(sb, 2048, 256, 3) : make_desc(sb, 16, 1024), db0 = make_desc(sb + 16384, 16, 1024);
    uint32_t eb = sb + OFF_BAR + 8 * BAR_HR;
    mbar_wait(fb + 8 * s, (phm >> s) & 1);
    if (first_bar) bar_sync(first_bar, 256);
#pragma unroll 1
    for (;;) {
        PROFK(pi++);
        const uint64_t da = da0 + (uint32_t)(s * 2048), db = db0 + (uint32_t)(s * 2048);
        wgmma_fence();
#pragma unroll
        for (int j = 0; j < 4; j++) {
            wgmma_n128<TA, 0>(acc[0], da + (TA ? 32 : 2) * j, db + 2 * j, j || !first);
            wgmma_n128<TA, 0>(acc[1], da + 512 + (TA ? 32 : 2) * j, db + 2 * j, j || !first);
        }
        wgmma_commit();
        first = false;
        phm ^= 1u << s;
        if (--n == 0) break;
        const uint32_t en = rel + 8 * s;
        if (++s == ns) s = 0;
        const uint32_t ok = mbar_test(fb + 8 * s, (phm >> s) & 1);
        wgmma_wait<1>();
        if (lead) mbar_arrive(eb);
        eb = en;
        if (!ok) mbar_wait(fb + 8 * s, (phm >> s) & 1);
        __syncwarp();
    }
    if (last_bar) bar_arrive(last_bar, 256);
    wgmma_wait<1>();
    if (lead) mbar_arrive(eb);
}

__global__ void __cluster_dims__(2, 1, 1) __launch_bounds__(384, 1)
fused_kernel(const __grid_constant__ CUtensorMap mapB, const __grid_constant__ CUtensorMap mapX,
             const __grid_constant__ CUtensorMap mapXs, const __grid_constant__ CUtensorMap mapU0,
             const __grid_constant__ CUtensorMap mapU2, const __grid_constant__ CUtensorMap mapXe,
             const __grid_constant__ CUtensorMap mapCre, const __grid_constant__ CUtensorMap mapCim,
             const __grid_constant__ CUtensorMap mapV, const __grid_constant__ CUtensorMap mapO,
             const __grid_constant__ CUtensorMap mapWr, const __grid_constant__ CUtensorMap mapWi,
             const __grid_constant__ CUtensorMap mapH,
             const __grid_constant__ Params P) {
    extern __shared__ __align__(1024) uint8_t sm[];
    const uint32_t sb = smem_u32(sm);
    const uint32_t bars = sb + OFF_BAR;
    const unsigned cl = blockIdx.x >> 1;
    const int role = cl < 4 ? 32 + 8 * cl : cl < 36 ? ((cl - 4) & 24) + ((cl - 5) & 7) : cl < 64 ? 33 + (cl - 36) / 7 * 8 + (cl - 30) % 7 : cl;
    const int b = role * 2 + (blockIdx.x & 1), tid = threadIdx.x, warp = __shfl_sync(0xffffffffu, tid >> 5, 0), lane = tid & 31;
    const bool main_cta = b < 128;
    if (b == 129) return;
    const int rp = (b >> 1) & 3, mq = ((b >> 3) & 2) + (b & 1), dt = ((b >> 1) & 4) + (b >> 5), tc = 4 * rp + mq;
    const int cls = b == 128 ? 128 : (b & 31) ? (b & 31) + 64 * (b >> 5) : (b == 64 ? 32 : b == 32 ? 64 : b);
    if (warp != 8 && elect()) {
        if (warp == 11) PROFG(0);
        const int u = warp - (warp > 8);
        asm volatile("prefetch.tensormap [%0];" :: "l"(&mapB + 2 + u) : "memory");
        mbar_init(bars + 8 * (5 + u), 1);
        mbar_init(bars + 8 * (16 + u), u ? 4 : 1);
        mbar_init(bars + 8 * (27 + u), u < 1 ? 4 : u == 6 ? 8 : (u == 7 || u == 8) ? 64 : 1);
        fence_barrier_init();
        fence_proxy_async_smem();
    }
    __syncwarp();
    const bool real_cls = (cls & 127) == 0;
    const int t = tid & 127;
    auto load_epoch = [&]() {
        unsigned e;
        asm volatile("ld.relaxed.gpu.global.u32 %0, [%1];" : "=r"(e) : "l"(&g_cnt[CNT_EPOCH * CS]));
        return e + 1;
    };
    const int g = lane >> 2, q = lane & 3;

    if (warp < 8) {
        reg_alloc<REG_M>();
        const int wg = warp >> 2, w = warp & 3;
        if (tid == 0) PROFX(94);
        bar_sync(0, 384);
        if (tid == 224) PROFG(8);
        auto kept = [&](int i) { uint64_t v; asm volatile("ld.volatile.shared.u64 %0, [%1];" : "=l"(v) : "r"(sb + OFF_KEPT + 8 * i) : "memory"); return v; };
        const uint32_t fb = bars + 8 * (BAR_FULL + 5 * wg);
        uint32_t phm = 0;
        const bool lead = lane == 0;
        const uint32_t rel = bars + 8 * BAR_EMPTY;
        if (wg) {
            {
                const int pp = (dt * 64 + 8 * (t & 64) + (t & 63)) & 1023;
                const uint32_t lr_ = ldg16(P.lam_re + pp), li_ = ldg16(P.lam_im + pp), ld_ = ldg16(P.log_dt + pp);
                const unsigned epoch = load_epoch();
                if (t < 64 && main_cta) g_agg[rp * 2048 + (dt + (t >> 5) * 8) * 128 + lane * 4 + mq] = make_uint4(0u, 0u, 0u, 0u);
                if (t < 4) asm volatile("st.shared.u64 [%0], %1;" :: "r"(sb + OFF_KEPT + 8 * lane),
                    "l"(lane == 0 ? (P.swapB ? 255ull : 127ull) | ((uint64_t)epoch << 32) : lane == 1 ? (uint64_t)g_agg : lane == 2 ? (uint64_t)(c_tab + 10240) : (uint64_t)&mapB) : "memory");
                const float lr = bf_lo(lr_), li = bf_lo(li_);
                const float dl = bf_round(expf(bf_lo(ld_)));
                const float mag = expf(dl * lr);
                float sn, cs; sincospif(dl * li * 0.31830988618379067f, &sn, &cs);
                const float2 l1 = make_float2(mag * cs, mag * sn);
                const float inv = 1.f / (lr * lr + li * li);
                const float2 cf = cmul(make_float2(l1.x - 1.f, l1.y), make_float2(lr * inv, -li * inv));
                sts128u(sb + OFF_K + 16 * t, __float_as_uint(l1.x), __float_as_uint(P.swapB ? -l1.y : l1.y), __float_as_uint(cf.x), __float_as_uint(cf.y));
                if (tid == 128) PROFX(92);
            }
            {
                const int kk = (t >> 3) & 7, r = t & 7;
                float sn, cs;
                sincospif((float)(((cls + 256 * kk) * r) & 2047) * (1.f / 1024.f), &sn, &cs);
                sn *= 1.f / 1024.f; cs *= 1.f / 1024.f;
                const uint32_t gf = sb + OFF_G + kk * 16 + r * 2, gi = sb + OFF_G + 512 + r * 16 + (kk & 1) * 128 + (kk & 6);
                if (t < 64) {
                    sts16(gf, cs); sts16(gf + 128, real_cls ? 0.f : sn); sts16(gf + 256, -sn); sts16(gf + 384, real_cls ? 0.f : cs);
                    sts16(gi, cs); sts16(gi + 8, -sn); sts16(gi + 256, sn); sts16(gi + 264, cs);
                }
            }
            if (main_cta) {
                uint32_t fa[16][4];
                pause(T_FA);
#pragma unroll
                for (int i = 0; i < 16; i++) {
                    asm volatile("ld.global.nc.L1::no_allocate.v4.u32 {%0, %1, %2, %3}, [%4];" : "=r"(fa[i][0]), "=r"(fa[i][1]), "=r"(fa[i][2]), "=r"(fa[i][3]) : "l"((const uint4*)c_tab + i * 128 + t));
                }
                if (t == 0) PROFX(91);
                const uint32_t ua = sb + OFF_U + (lane >> 4) * 4096 + (8 * w + (lane & 7)) * 128 + ((((lane >> 3) & 1) ^ (lane & 7)) << 4);
                float acc[4][32];
                const uint64_t db = make_desc(sb + OFF_U, 8192, 1024);
                uint32_t x[4][8], y[4][8];
                float gp[4][4];
#pragma unroll
                for (int m = 0; m < 6; m++) {
                    if (m >= 2) {
                        const int n = m - 2;
                        if (m < 5) wgmma_wait<1>(); else wgmma_wait<0>();
#pragma unroll
                        for (int i = 0; i < 32; i++) asm volatile("" : "+f"(acc[n][i]) :: "memory");
                        asm volatile("" : "+f"(gp[n][0]), "+f"(gp[n][2]) :: "memory");
#pragma unroll
                        for (int j = 0; j < 8; j++) { x[n][j] = pack2(acc[n][4 * j], acc[n][4 * j + 1]); y[n][j] = pack2(acc[n][4 * j + 2], acc[n][4 * j + 3]); }
                    }
                    if (m < 4) {
                        mbar_wait(bars + 8 * (BAR_XC + m), 0);
                        if (t == 0 && m == 3) PROF(8);
                        wgmma_fence();
                        wgmma_rs_n64<0, 1>(acc[m], fa[4 * m], db + 512 * m);
#pragma unroll
                        for (int j = 1; j < 4; j++) wgmma_rs_n64<1, 1>(acc[m], fa[4 * m + j], db + 512 * m + 128 * j);
#pragma unroll
                        for (int j = 0; j < 4; j++) wgmma_n8(gp[m], make_desc(sb + OFF_U, 16, 1024) + 512 * m + 2 * j, make_desc(sb + OFF_GW, 16, 1024) + 2 * j, j);
                        wgmma_commit();
                    }
                }
                if (t < 4) {
#pragma unroll
                    for (int j = 0; j < 8; j++) {
                        const uint32_t s0 = bf_add2(x[0][j], x[2][j]), s2 = bf_add2(x[1][j], x[3][j]), ty = bf_sub2(y[1][j], y[3][j]), sy = bf_add2(y[1][j], y[3][j]);
                        const uint32_t b0 = y[0][j], b2 = y[2][j];
                        y[1][j] = bf_sub2(x[3][j], x[1][j]); x[1][j] = bf_sub2(x[0][j], x[2][j]);
                        x[0][j] = bf_add2(s0, s2); y[0][j] = bf_sub2(s0, s2);
                        x[2][j] = bf_add2(b0, ty); y[2][j] = bf_add2(sy, b2) ^ 0x80008000u;
                        x[3][j] = bf_sub2(b0, ty); y[3][j] = bf_sub2(b2, sy);
                    }
                } else {
#pragma unroll
                    for (int j = 0; j < 8; j++) {
                        const uint32_t s0x = bf_add2(x[0][j], x[2][j]), s1x = bf_sub2(x[0][j], x[2][j]), s2x = bf_add2(x[1][j], x[3][j]), tx = bf_sub2(x[1][j], x[3][j]);
                        const uint32_t s0y = bf_add2(y[0][j], y[2][j]), s1y = bf_sub2(y[0][j], y[2][j]), s2y = bf_add2(y[1][j], y[3][j]), ty = bf_sub2(y[1][j], y[3][j]);
                        x[0][j] = bf_add2(s0x, s2x); y[0][j] = bf_add2(s0y, s2y);
                        x[1][j] = bf_add2(s1x, ty); y[1][j] = bf_sub2(s1y, tx);
                        x[2][j] = bf_sub2(s0x, s2x); y[2][j] = bf_sub2(s0y, s2y);
                        x[3][j] = bf_sub2(s1x, ty); y[3][j] = bf_add2(s1y, tx);
                    }
                }
                helper_sync();
                if (q == 0) {
#pragma unroll
                    for (int i = 0; i < 2; i++)
                        sts128u(sb + OFF_GW + (16 * w + 8 * i + g) * 16, __float_as_uint(gp[0][2 * i]), __float_as_uint(gp[1][2 * i]), __float_as_uint(gp[2][2 * i]), __float_as_uint(gp[3][2 * i]));
                }
#pragma unroll
                for (int c = 0; c < 4; c++)
#pragma unroll
                    for (int j = 0; j < 8; j += 2) stsm_x4((ua ^ (j << 4)) + c * 8192, x[c][j], x[c][j + 1], y[c][j], y[c][j + 1]);
                if (t == 0) PROF(21);
            }
            fence_proxy_async_smem();
            __syncwarp();
            if (lane == 0) mbar_arrive(bars + 8 * BAR_S1);
        }
        uint4 tw[4];
        auto load_tw = [&]() {
            const uint4* twp = (const uint4*)kept(2) + t;
#pragma unroll
            for (int i = 0; i < 4; i++) tw[i] = ldg128(twp + (i < 2 ? i ^ wg : i & 1) * 128);
        };
        {
            float acc[2][64];
            float2 lam8[2], lam32[2], lam64[2], wq[2], w4[2], l32q[2], ex[2];
            float2 ag[2][4];
            if (main_cta) {
                int sp = wg * SLOT_OF(16);
                ring_steps<0>(acc, sb, fb, 16, 5 - wg, sp, phm, true, lead, rel, 2 * wg, 2 + wg, 16 * wg);
                mbar_wait(bars + 8 * BAR_S1, 0);
                const uint4* ap = (const uint4*)kept(1) + (((tc - 1 - q) >> 2) * 2048 + (dt + 8 * wg) * 128 + t);
                const uint64_t k0 = kept(0);
                const uint32_t fl = (uint32_t)k0, tag = ((uint32_t)(k0 >> 32) & 7) | 8;
                const bool swapB = fl & 128;
                float2 lam1[2], coef[2];
#pragma unroll
                for (int i = 0; i < 2; i++) {
                    const uint4 kv = lds128u(sb + OFF_K + (64 * wg + 32 * i + (t >> 2)) * 16);
                    lam1[i] = make_float2(__uint_as_float(kv.x), __uint_as_float(kv.y));
                    coef[i] = make_float2(__uint_as_float(kv.z), __uint_as_float(kv.w));
                    float2 z = cmul(lam1[i], lam1[i]);
                    z = cmul(z, z);
                    lam8[i] = cmul(z, z);
                    z = cmul(lam8[i], lam8[i]);
                    lam32[i] = cmul(z, z); lam64[i] = cmul(lam32[i], lam32[i]);
                    const float2 l128 = cmul(lam64[i], lam64[i]), l256 = cmul(l128, l128), one = make_float2(1.f, 0.f);
                    w4[i] = cmul(l256, l256);
                    wq[i] = cmul(((tc - 1 - q) & 1) ? l128 : one, ((tc - 1 - q) & 2) ? l256 : one);
                    l32q[i] = cmul((q & 1) ? lam32[i] : one, (q & 2) ? lam64[i] : one);
                    asm volatile("" : "+f"(w4[i].x), "+f"(w4[i].y), "+f"(wq[i].x), "+f"(wq[i].y), "+f"(l32q[i].x), "+f"(l32q[i].y));
                }
                sched_fence();
                wgmma_wait_all(acc[0]);
#pragma unroll
                for (int o = 0; o < 64; o++) asm volatile("" : "+f"(acc[1][o]) :: "memory");
                if (lead) mbar_arrive(rel + 8 * (sp));
                if (tid == 0) PROF(3);
                if (tid == 128) PROF(25);
                if (tid == 224) PROFG(12);
                float2 v[2];
#pragma unroll
                for (int c = 0; c < 8; c++) ag[c >> 2][c & 3] = make_float2(acc[c >> 2][16 * (c & 3)], acc[c >> 2][16 * (c & 3) + 2]);
#pragma unroll
                for (int r = 1; r < 8; r++)
#pragma unroll
                    for (int c = 0; c < 8; c++) {
                        const int i = c >> 2, o = 16 * (c & 3) + 4 * (r >> 1) + (r & 1);
                        ag[i][c & 3] = cfma(lam1[i], ag[i][c & 3], make_float2(acc[i][o], acc[i][o + 2]));
                    }
#pragma unroll
                for (int i = 0; i < 2; i++) {
                    v[i] = ag[i][0];
#pragma unroll
                    for (int c = 1; c < 4; c++) v[i] = cfma(lam8[i], v[i], ag[i][c]);
                    float2 n = make_float2(__shfl_up_sync(0xffffffffu, v[i].x, 1, 4), __shfl_up_sync(0xffffffffu, v[i].y, 1, 4));
                    if (q >= 1) v[i] = cfma(lam32[i], n, v[i]);
                    n = make_float2(__shfl_up_sync(0xffffffffu, v[i].x, 2, 4), __shfl_up_sync(0xffffffffu, v[i].y, 2, 4));
                    if (q >= 2) v[i] = cfma(lam64[i], n, v[i]);
                }
                if (q == 3 && tc < 15) {
                    asm volatile("{\n.reg .b64 a, b;\nmov.b64 a, {%1, %2};\nmov.b64 b, {%3, %4};\nst.relaxed.gpu.global.v2.b64 [%0], {a, b};\n}"
                        :: "l"(ap + (2045 + mq)), "r"((__float_as_uint(v[0].x) & ~15u) | tag), "r"(__float_as_uint(v[0].y)),
                           "r"((__float_as_uint(v[1].x) & ~15u) | tag), "r"(__float_as_uint(v[1].y)) : "memory");
                }
                PROFS(72 + 8 * wg);
                sched_fence();
                {
                    float m00[2], m01[2], m10[2], m11[2];
                    auto scale = [&](int i, float& x, float& y) { const float u = fmaf(m00[i], x, m01[i] * y); y = fmaf(m10[i], x, m11[i] * y); x = u; };
#pragma unroll
                    for (int i = 0; i < 2; i++) {
                        ex[i] = make_float2(__shfl_up_sync(0xffffffffu, v[i].x, 1, 4), __shfl_up_sync(0xffffffffu, v[i].y, 1, 4));
                        if (q == 0) ex[i] = make_float2(0.f, 0.f);
                        const float cx = coef[i].x, cy = coef[i].y;
                        m00[i] = cx; m01[i] = -cy; m10[i] = -cy; m11[i] = -cx;
                        if (swapB) { m00[i] = -cy; m01[i] = cx; m10[i] = -cx; m11[i] = -cy; }
                        scale(i, ex[i].x, ex[i].y);
                        scale(i, l32q[i].x, l32q[i].y);
                        if (!swapB) { lam1[i].y = -lam1[i].y; lam8[i].y = -lam8[i].y; }
#pragma unroll
                        for (int o = 0; o < 64; o += 4) {
                            scale(i, acc[i][o], acc[i][o + 2]); scale(i, acc[i][o + 1], acc[i][o + 3]);
                            if ((o + 4) % SCB == 0) {
#pragma unroll
                                for (int u = o + 4 - SCB; u < o + 4; u++) asm volatile("" : "+f"(acc[i][u]));
                                sched_fence();
                            }
                        }
#pragma unroll
                        for (int c = 0; c < 3; c++) scale(i, ag[i][c].x, ag[i][c].y);
                    }
                }
                PROFS(73 + 8 * wg);
                uint4 rr[4];
#pragma unroll
                for (int n = 0; n < 4; n++) rr[n] = make_uint4(tag, 0u, tag, 0u);
                auto poll = [&]() {
#pragma unroll
                    for (int n = 0; n < 4; n++)
                        asm volatile("{\n.reg .b64 a, b;\n.reg .pred p;\nsetp.lt.s32 p, %5, %6;\nmov.b64 a, {%0, %1};\nmov.b64 b, {%2, %3};\n"
                                     "@p ld.relaxed.gpu.global.v2.b64 {a, b}, [%4];\nmov.b64 {%0, %1}, a;\nmov.b64 {%2, %3}, b;\n}"
                            : "+r"(rr[n].x), "+r"(rr[n].y), "+r"(rr[n].z), "+r"(rr[n].w) : "l"(ap - 2048 * n), "r"(4 * n), "r"(tc - q) : "memory");
                };
                poll();
#pragma unroll 1
                for (unsigned n = 0; n < SPIN_LIMIT; n++) {
                    uint32_t bad = 0;
#pragma unroll
                    for (int j = 0; j < 4; j++) bad |= (rr[j].x ^ tag) | (rr[j].z ^ tag);
                    if (!__any_sync(0xffffffffu, bad & 15)) break;
                    if (n < 3) PROFS(74 + 8 * wg + n);
                    poll();
                }
                float2 part[2] = {make_float2(__uint_as_float(rr[3].x), __uint_as_float(rr[3].y)), make_float2(__uint_as_float(rr[3].z), __uint_as_float(rr[3].w))};
#pragma unroll
                for (int n = 2; n >= 0; n--) {
                    part[0] = cfma(w4[0], part[0], make_float2(__uint_as_float(rr[n].x), __uint_as_float(rr[n].y)));
                    part[1] = cfma(w4[1], part[1], make_float2(__uint_as_float(rr[n].z), __uint_as_float(rr[n].w)));
                }
#pragma unroll
                for (int i = 0; i < 2; i++) {
                    part[i] = cmul(wq[i], part[i]);
                    part[i].x += __shfl_xor_sync(0xffffffffu, part[i].x, 1); part[i].y += __shfl_xor_sync(0xffffffffu, part[i].y, 1);
                    part[i].x += __shfl_xor_sync(0xffffffffu, part[i].x, 2); part[i].y += __shfl_xor_sync(0xffffffffu, part[i].y, 2);
                    if (!swapB) part[i].y = -part[i].y;
                    ex[i] = cfma(l32q[i], part[i], ex[i]);
#pragma unroll
                    for (int c = 0; c < 4; c++) { const float2 n = cfma(lam8[i], ex[i], ag[i][c]); ag[i][c] = ex[i]; ex[i] = n; }
                }
                if (t == 0) PROF(4 + 25 * wg);
                const uint32_t hs = sb + OFF_HS + (lane >> 4) * 1024 + w * 256 + (lane & 7) * 32 + (((lane << 1) ^ (lane << 2)) & 16);
#pragma unroll
                for (int i = 0; i < 2; i++) {
                    if (fl & (4 << i)) {
#pragma unroll
                        for (int r = 0; r < 8; r++)
#pragma unroll
                            for (int c = 0; c < 4; c++) {
                                const int o = 16 * c + 4 * (r >> 1) + (r & 1);
                                ag[i][c] = cfma(lam1[i], ag[i][c], make_float2(acc[i][o], acc[i][o + 2]));
                                acc[i][o] = ag[i][c].x; acc[i][o + 2] = ag[i][c].y;
                            }
                    }
                    if (i) {
                        fence_proxy_async_smem();
                        __syncwarp();
                        if (lane == 0) mbar_arrive(bars + 8 * BAR_HW);
                    }
                    mbar_wait(bars + 8 * (wg ? (i ? BAR_WR : BAR_HD) : BAR_EMPTY + 4), 0);
#pragma unroll
                    for (int z = 0; z < 8; z++) {
                        const float* a = &acc[i][2 * z];
                        stsm_x4(hs + i * (16384 + wg * 18432) + (z & 1) * 8192 + (z >> 1) * 2048, pack2(a[0], a[32]), pack2(a[16], a[48]), pack2(a[1], a[33]), pack2(a[17], a[49]));
                    }
                }
                fence_proxy_async_smem();
                __syncwarp();
                if (lane == 0) mbar_arrive(bars + 8 * (BAR_HW + 1));
                load_tw();
                if (t == 0) PROF(5 + 25 * wg);
            } else {
                mbar_wait(bars + 8 * BAR_S1, 0);
                load_tw();
            }
        }
        if (wg) mbar_wait(bars + 8 * BAR_WR, 0);
#pragma unroll 1
        for (int ps = wg; ps < 1 + 2 * wg; ps++) {
            if (ps != 1) {
                mbar_wait(bars + (ps ? 8 * BAR_CD : 8 * BAR_U), 0);
                if (t == 0) PROF(ps ? 7 : 23);
                radix8(sb, ps, w, lane, 5 + wg);
                if (t == 0) PROF(ps ? 24 : 22);
                if (ps) break;
                fence_proxy_async_smem();
                bar_sync(5, 128);
            }
            mbar_wait(bars + 8 * (BAR_C + ps), 0);
            phase_c(sb, ps, b + ps == 0, w, lane, tw);
            fence_proxy_async_smem();
            __syncwarp();
            if (lane == 0) {
                mbar_arrive(bars + 8 * BAR_CD);
                if (!wg) mbar_arrive(bars + 8 * BAR_WR);
            }
        }
        if (wg == 0) {
            if (main_cta) {
                float acc[2][64];
                int s = SLOT_OF(32);
                ring_steps<1>(acc, sb, fb, 30, NS, s, phm, true, lead, rel, 3, 0, 32);
                auto full = [&](int k) { mbar_wait(fb + 8 * SLOT_OF(k), (phm >> SLOT_OF(k)) & 1); PROFK(k); };
                auto hstep = [&](int k, int i) {
                    const uint64_t da = make_desc(sb + SLOT_OF(k) * SLOT + i * 8192, 2048, 256, 3), db = make_desc(sb + SLOT_OF(k) * SLOT + 16384, 16, 1024);
                    if (k == 62 || !i) wgmma_fence();
#pragma unroll
                    for (int j = 0; j < 4; j++) wgmma_n128<1, 0>(acc[i], da + 32 * j, db + 2 * j, 1);
                };
                auto vstep = [&](int k, int i) {
                    const uint64_t da = make_desc(sb + OFF_U - i * 32768 + k * 8192, 16, 1024), db = make_desc(sb + SLOT_OF(63 + (k >> 1)) * SLOT + (k & 1) * 16384, 8192, 1024);
                    wgmma_fence();
#pragma unroll
                    for (int j = 0; j < 4; j++) wgmma_n128<0, 1>(acc[i], da + 2 * j, db + 128 * j, 1);
                };
                full(62);
                hstep(62, 0);
                wgmma_commit();
                wgmma_wait<1>();
                if (lead) mbar_arrive(rel + 8 * (SLOT_OF(61)));
                __syncwarp();
                bar_sync(4, 256);
#pragma unroll
                for (int k = 0; k < 4; k++) {
                    if (!(k & 1)) full(63 + (k >> 1));
                    vstep(k, 0);
                }
                full(65);
                hstep(65, 0);
                wgmma_commit();
                const CUtensorMap* maps = (const CUtensorMap*)kept(3);
                const uint32_t ob = sb + OFF_U + w * 2048, oa = ob + g * 256 + (((q >> 1) ^ (2 * g & 6)) << 4) + (q & 1) * 8;
#pragma unroll
                for (int i = 0; i < 2; i++) {
                    uint4 e[8];
                    const uint2 sc = lds64u(sb + OFF_SC + (64 * i + 16 * w + 2 * g) * 4);
#pragma unroll
                    for (int j = 0; j < 8; j++) e[j] = lds128u(sb + OFF_HS + (8 * i + j) * 2048 + t * 16);
                    if (i) wgmma_wait<0>();
                    else {
                        hstep(62, 1);
                        hstep(65, 1);
                        wgmma_commit();
                        wgmma_wait<1>();
                    }
#pragma unroll
                    for (int o = 0; o < 64; o++) asm volatile("" : "+f"(acc[i][o]) :: "memory");
                    if (tid == 0) PROF(17 + i);
                    if (tid == 96 && i) PROFG(20);
#pragma unroll
                    for (int c = 0; c < 4; c++) {
#pragma unroll
                        for (int j = 0; j < 8; j++) {
                            const int o = 16 * c + 2 * j;
                            const uint4 e4 = e[2 * c + (j >> 2)];
                            const uint32_t ev = (j & 2) ? ((j & 1) ? e4.w : e4.z) : ((j & 1) ? e4.y : e4.x);
                            const float f = __uint_as_float((j & 1) ? sc.y : sc.x);
                            sts64((oa ^ ((j >> 1) << 5) ^ ((j & 1) * 144)) + c * 8192 - i * 32768, fmaf(f, acc[i][o], bf_lo(ev)), fmaf(f, acc[i][o + 1], bf_hi(ev)));
                        }
                        fence_proxy_async_smem();
                        __syncwarp();
                        if (elect()) tma_store_3d(maps + 9, ob + c * 8192 - i * 32768, 128 * dt + 32 * c, 128 * (tc & 1) + 64 * i + 16 * w, tc >> 1);
                        if (!i) {
                            __syncwarp();
                            vstep(c, 1);
                            if (c == 3) wgmma_commit();
                        }
                    }
                }
                if (elect()) {
                    bulk_commit();
                    bulk_wait_read();
                }
                if (tid == 0) PROF(19);
                if (tid == 96) { PROF(20); PROFG(4); }
            }
        } else {
            fence_proxy_async_smem();
            __syncwarp();
            if (lane == 0) mbar_arrive(bars + 8 * BAR_VW);
            __syncwarp();
            if (tid == 224) PROFG(16);
            if (main_cta) {
                uint32_t tv[40];
                {
                    float gs[16];
                    uint32_t dk[16], sk[64];
#pragma unroll
                    for (int j = 0; j < 16; j++) gs[j] = __ldcg(g_gp + (16 * (tc >> 1) + j) * 256 + 128 * (tc & 1) + t);
#pragma unroll
                    for (int j = 0; j < 16; j++) dk[j] = ldg32u(P.dskip + 128 * dt + 8 * j + 2 * q);
#pragma unroll
                    for (int j = 0; j < 10; j++) {
                        const uint4 v = ldg128((const uint4*)c_inv + (tc & 1) * 1280 + j * 128 + t);
                        tv[4 * j] = v.x; tv[4 * j + 1] = v.y; tv[4 * j + 2] = v.z; tv[4 * j + 3] = v.w;
                    }
#pragma unroll
                    for (int j = 0; j < 4; j++) gs[j] = (gs[j] + gs[j + 4]) + (gs[j + 8] + gs[j + 12]);
                    gs[0] = (gs[0] + gs[1]) + (gs[2] + gs[3]);
                    const float gg = bf_round(__fdividef(1.f, 1.f + __expf(-bf_round(gs[0])))), og = bf_round(1.f - gg), o2 = fmaxf(2.f * og, 0x1p-40f);
                    sts32(sb + OFF_SC + 4 * t, __float_as_uint(o2));
                    sts32(sb + OFF_SC + 512 + 4 * t, pack2(__fdividef(gg, o2), og));
                    bar_sync(6, 128);
                    mbar_wait(bars + 8 * BAR_X, 0);
                    const uint32_t xa = sb + OFF_HS + (16 * w + (lane & 15)) * 128 + (((lane >> 4) ^ (lane & 7)) << 4);
#pragma unroll
                    for (int e = 0; e < 2; e++) {
                        const uint2 u = lds64u(sb + OFF_SC + 512 + (64 * e + 16 * w + 2 * g) * 4);
                        const uint32_t o0 = __byte_perm(u.x, 0, 0x3232), o1 = __byte_perm(u.y, 0, 0x3232);
#pragma unroll
                        for (int j = 0; j < 8; j++) {
                            uint32_t x[4];
                            ldsm_x4(x, (xa ^ ((j & 3) << 5)) + e * 8192 + (j >> 2) * 34816);
#pragma unroll
                            for (int c = 0; c < 4; c++) {
                                sk[32 * e + 4 * j + c] = bf_mul2(bf_mul2(x[c], dk[2 * j + (c >> 1)]), (c & 1) ? o1 : o0);
                                asm volatile("" : "+r"(sk[32 * e + 4 * j + c]));
                            }
                        }
                    }
                    if (t == 0) PROFX(95);
                    bar_sync(6, 128);
#pragma unroll
                    for (int j = 0; j < 16; j++) sts128u(sb + OFF_HS + j * 2048 + t * 16, sk[4 * j], sk[4 * j + 1], sk[4 * j + 2], sk[4 * j + 3]);
                }
                if (t == 0) PROF(15);
                const uint32_t mq4 = ((t >> 2) & 2) + (t >> 6), sel = (t & 64) ? 0x1032 : 0x3210;
#pragma unroll
                for (int e = 1; e >= 0; e--) {
                    uint32_t f[4];
#pragma unroll
                    for (int j = 0; j < 4; j++) f[j] = lds16(sb + OFF_SC + 512 + (64 * e + 16 * j + ((t >> 2) & 14) + (t >> 6)) * 4) * 0x10001u;
                    if (!e) mbar_wait(bars + 8 * BAR_U, 1);
#pragma unroll
                    for (int j = 0; j < 16; j++) {
                        const int k = j & 3, r = j >> 2;
                        const uint32_t fk = f[r] ^ (((k * mq4 + 1) & 2) << 30) ^ (((k * mq4) & 2) << 14);
                        uint32_t o[3];
#pragma unroll
                        for (int u = 0; u < 3; u++) { const uint32_t v = tv[16 + 12 * e + 3 * r + u]; o[u] = bf_mul2((k & 1) ? __byte_perm(v, 0, sel) : v, fk); }
                        sts128u(sb + OFF_U - e * 32768 + (4 * k + r) * 2048 + t * 16, bf_mul2(tv[j], f[r]), o[0], o[1], o[2]);
                    }
                }
                fence_proxy_async_smem();
                bar_arrive(4, 256);
                if (t == 0) PROF(16);
            }
            if (t == 0) {
                const unsigned old = atomicAdd(&g_cnt[CNT_DONE * CS], 1u);
                if (old == 128) { g_cnt[CNT_DONE * CS] = 0; g_cnt[CNT_EPOCH * CS] = (uint32_t)(kept(0) >> 32); }
            }
        }
    } else {
        reg_dealloc<REG_H>();
        const int w = warp - 8;
        if (w == 0) {
            if (elect()) {
                PROF(0);
#pragma unroll
                for (int i = 0; i < 5; i++) mbar_init(bars + 8 * i, 1);
                fence_barrier_init();
                fence_proxy_async_smem();
                PROFX(88);
            }
            __syncwarp();
            bar_arrive(0, 384);
            if (elect()) {
                if (main_cta) {
#pragma unroll 1
                    for (int k = 0; k < 5; k++) {
                        const uint32_t full = bars + 8 * (BAR_FULL + k), st = sb + k * SLOT;
                        mbar_expect_tx(full, SLOT);
                        tma_load_4d(st, &mapB, full, k * 64, 0, 0, dt * 8);
                        tma_load_4d(st + 16384, &mapX, full, k * 64, 0, 0, tc * 64);
                        if (k == 0) PROFX(89);
                        if (P_R0) pause(P_R0);
                    }
                }
                PROF(27);
            }
            __syncwarp();
            bar_sync(7, 64);
            if (main_cta && elect()) {
                int s = 0; uint32_t ph = 0;
#pragma unroll 1
                for (int k = 5; k < 66; k++) {
                    mbar_wait(bars + 8 * (BAR_EMPTY + s), ph);
                    const uint32_t st = sb + s * SLOT;
                    const uint32_t full = bars + 8 * (BAR_FULL + s + ((k >> 4) == 1 ? 5 : 0));
                    mbar_expect_tx(full, SLOT);
                    if (k < 32) {
                        tma_load_4d(st + 16384, &mapX, full, (k & 15) * 64, 0, 0, tc * 64);
                        tma_load_4d(st, &mapB, full, (k & 15) * 64, 0, 0, dt * 8 + (k >> 4) * 64);
                    } else if (k < 63 || k == 65) {
                        const int h = min(k - 32, 31);
                        tma_load_3d(st + 16384, &mapCre + (h & 1), full, 0, dt * 128, h >> 1);
                        if ((h & 15) == 0) mbar_wait(bars + 8 * (BAR_F + (h >> 4)), 0);
                        bulk_load(st, g_hT + (h * 16 + tc) * 16384, 16384, full);
                    } else {
                        mbar_wait(bars + 8 * (BAR_F + 2), 0);
                        tma_load_3d(st, &mapV, full, 0, (k & 64) * 2, (tc >> 1) * 16 + dt * 2);
                        tma_load_3d(st + 16384, &mapV, full, 0, (k & 64) * 2 + 64, (tc >> 1) * 16 + dt * 2);
                    }
                    if (++s == (k < 15 ? 5 : NS)) { s = 0; ph ^= 1; }
                }
            }
        } else {
            const unsigned epoch = load_epoch();
            bar_sync(0, 384);
            if (w == 1) {
                bar_arrive(7, 64);
                if (elect()) {
                    if (main_cta) {
                        pause(T_XS);
                        bulk_load(sb + OFF_GW, P.gate_w + (b & 15) * 64, 128, bars + 8 * BAR_XC);
#pragma unroll 1
                        for (int c = 0; c < 4; c++) {
                            mbar_expect_tx(bars + 8 * (BAR_XC + c), c ? 8192 : 8192 + 128);
                            tma_load_4d(sb + OFF_U + c * 8192, &mapXs, bars + 8 * (BAR_XC + c), (b & 15) * 64, 0, c, b >> 4);
                            pause(P_XS);
                        }
                    }
                    mbar_wait(bars + 8 * BAR_S1, 0);
                    if (main_cta) {
#pragma unroll
                        for (int c = 0; c < 4; c++) {
                            if (c) pause(PACE_U);
                            tma_store_4d(&mapU0, sb + OFF_U + c * 8192, (b & 15) * 64, 32 * c, 0, b >> 4);
                        }
                        bulk_store(g_gp + b * 256, sb + OFF_GW, 1024);
                        bulk_commit();
                        bulk_wait0();
                        signal_counter(&g_cnt[CNT_U * CS]);
                    }
                    PROF(9);
                    mbar_expect_tx(bars + 8 * BAR_U, 32768);
                    wait_counter(&g_cnt[CNT_U * CS], epoch * 128);
                    PROF(11);
#pragma unroll
                    for (int i = 0; i < 8; i++) {
                        if (PACE_L && i && !(i & 1)) pause(PACE_L);
                        tma_load_4d(sb + OFF_U + i * 4096, &mapU2, bars + 8 * BAR_U, 0, 0, (i & 3) * 4, b == 128 ? 1 : b == 0 ? 0 : 2 * b + (i >> 2));
                    }
                    if (main_cta) {
#pragma unroll 1
                        for (int i = 0; i < 2; i++) {
#pragma unroll 1
                            for (int j = 0; j < 2 * HN; j++) {
                                const int hf = j / HN, jj = j % HN;
                                if (jj == 0) mbar_wait(bars + 8 * (BAR_HW + hf), i);
                                if (j) pause(i ? PACE_HB : PACE_HA);
                                tma_store_3d(&mapH, sb + OFF_HS + hf * (16384 + i * 18432) + jj * (16384 / HN), 0, 2 * tc + hf, (dt + 8 * i) * 16 + jj * (16 / HN));
                            }
                            bulk_commit();
                            bulk_wait0();
                            signal_counter(&g_cnt[(CNT_H + i) * CS]);
                            mbar_arrive(bars + 8 * (BAR_HD + i));
                            PROF(i ? 6 : 26);
                            wait_counter(&g_cnt[(CNT_H + i) * CS], epoch * 128);
                            mbar_arrive(bars + 8 * (BAR_F + i));
                            PROF(1 + i);
                        }
                    }
                }
            } else {
                const int ld = (1026 * cls) >> 7, lm = (1026 * ((256 - cls) & 255)) >> 7;
                if (elect() && main_cta) {
                    if (w == 3) {
                        pause(T_W);
#pragma unroll 1
                        for (int i = 0; i < 8; i++) {
                            tma_prefetch_4d(&mapWr + (i & 1), 0, (i & 2) ? lm : ld, i >> 2, 0);
                            pause(200);
                        }
                        bulk_prefetch_l2(c_inv + b * 40, 320);
                    } else {
                        pause(T_BA + D_XS * tc);
                        if (tc > 4) tma_prefetch_4d(&mapB, tc * 64, 0, 0, dt * 8);
                        pause(T_B2);
                        bulk_prefetch_l2(((b & 1) ? P.b_im : P.b_re) + (64 + (b >> 1)) * 8192, 16384);
                        pause(T_W0 - D_XS * tc);
                    }
                }
#pragma unroll 1
                for (int ps = 0; ps < 2; ps++) {
                    const uint32_t wb = sb + OFF_W + (1 - ps) * 18432;
                    if (w == 2 && elect()) {
                        const uint32_t bw = bars + 8 * (BAR_W + ps);
                        if (ps && main_cta) mbar_wait(bars + 8 * BAR_HD, 0);
                        mbar_expect_tx(bw, ps ? 18432 : 18432 + 8192);
#pragma unroll 1
                        for (int i = 0; i < 4; i++) {
                            tma_load_4d(wb + (i >> 1) * 4608 + (i & 1) * 9216, &mapWr + (i & 1), bw, 0, i < 2 ? ld : lm, (i < 2 || b == 0) ? ps : 1 - ps, 0);
                            pause(P_W);
                        }
                        if (!ps) bulk_load(sb + OFF_F, c_tab + 8192, 8192, bw);
                        PROFX(85 + ps);
                    }
                    if (w == 3 && ps && main_cta && elect()) {
#pragma unroll 1
                        for (int i = 0; i < 8; i++) {
                            bulk_prefetch_l2(((b & 1) ? P.c_im : P.c_re) + (size_t)(b >> 1) * 16384 + i * 2048, 4096);
                            pause(P_C);
                        }
                    }
                    __syncwarp();
                    mbar_wait(bars + 8 * (BAR_W + ps), 0);
                    if (tid == 320) PROF(ps ? 31 : 10);
#pragma unroll 1
                    for (int u = 0; u < 4; u++) {
                        const int row = 2 * (w - 2) + (u >> 1), pl = u & 1;
                        const uint32_t dp = wb + pl * 9216 + row * 1152, mp = wb + pl * 9216 + 4608 + ((b == 0 && ps == 0) ? (4 - row) & 3 : 3 - row) * 1152;
                        const uint32_t od = dp + ((1026 * cls) & 127), om = mp + ((1026 * (256 - cls)) & 127);
                        uint32_t v[4][8], o[4][4];
#pragma unroll
                        for (int i = 0; i < 8; i++) {
                            const uint4 r = lds128u((i < 4 ? (od & ~15u) + 16 * lane + (i >> 1) * 512 : ((om + 1010) & ~15u) - 16 * lane - ((i >> 1) & 1) * 512) + (i & 1) * 16);
                            uint32_t* d = &v[i >> 1][4 * (i & 1)];
                            d[0] = r.x; d[1] = r.y; d[2] = r.z; d[3] = r.w;
                        }
                        const uint32_t e0 = lds16(om), e1 = lds16(od + 1024);
                        auto fwd = [&](int ws) {
#pragma unroll
                            for (int k = 0; k < 8; k++) o[k >> 2][k & 3] = __byte_perm(v[k >> 2][ws + (k & 3)], v[k >> 2][ws + (k & 3) + 1], (cls & 1) ? 0x5432 : 0x3210);
                        };
                        auto mir = [&](int ws) {
#pragma unroll
                            for (int k = 8; k < 16; k++) o[k >> 2][k & 3] = __byte_perm(v[k >> 2][ws + 3 - (k & 3)], v[k >> 2][ws + 4 - (k & 3)], (cls & 1) ? 0x1032 : 0x3254);
                        };
                        switch ((cls >> 1) & 3) { case 0: fwd(0); break; case 1: fwd(1); break; case 2: fwd(2); break; default: fwd(3); }
                        switch (((1 - cls) >> 1) & 3) { case 0: mir(0); break; case 1: mir(1); break; case 2: mir(2); break; default: mir(3); }
                        if (lane == 0) {
                            o[0][0] = pack2(fmaf(pl ? -0.5f : 0.5f, bf_lo(e0), 0.5f * bf_lo(o[0][0])), bf_hi(o[0][0]));
                            o[2][0] = pack2(fmaf(pl ? -0.5f : 0.5f, bf_lo(e1), 0.5f * bf_lo(o[2][0])), bf_hi(o[2][0]));
                        }
                        __syncwarp();
#pragma unroll
                        for (int i = 0; i < 4; i++)
                            sts128u((i < 2 ? dp : mp) + (i & 1) * 512 + ((lane * 16) ^ ((lane << 1) & 48)), o[i][0], o[i][1], o[i][2], o[i][3]);
                    }
                    if (ps) fence_proxy_async_smem();
                    mbar_arrive(bars + 8 * (BAR_C + ps));
                    if (tid == 320) PROF(ps ? 12 : 28);
                }
                if (elect()) {
                    if (w == 3) {
                        if (main_cta) {
                            mbar_wait(bars + 8 * (BAR_HD + 1), 0);
                            mbar_expect_tx(bars + 8 * BAR_X, 32768);
#pragma unroll 1
                            for (int i = 0; i < 4; i++) {
                                pause(P_XE);
                                tma_load_5d(sb + OFF_HS + (i & 1) * 8192 + (i >> 1) * 34816, &mapXe, bars + 8 * BAR_X, 128 * dt + 64 * (i >> 1), 8 * (tc & 1) + 4 * (i & 1), tc >> 1);
                            }
                        }
                    } else {
                        mbar_wait(bars + 8 * BAR_VW, 0);
#pragma unroll 1
                        for (int i = 0; i < (real_cls ? 4 : 8); i++) {
                            if (i) pause(PACE_V);
                            tma_store_4d(&mapU2, sb + OFF_U + i * 4096, 0, 0, (i & 3) * 4, b == 128 ? 1 : 2 * b + (i >> 2));
                        }
                        bulk_commit();
                        bulk_wait_read();
                        mbar_arrive(bars + 8 * BAR_U);
                        bulk_wait0();
                        signal_counter(&g_cnt[CNT_V * CS]);
                        PROF(13);
                        if (main_cta) {
                            wait_counter(&g_cnt[CNT_V * CS], epoch * 129);
                            mbar_arrive(bars + 8 * (BAR_F + 2));
                            PROF(14);
                        }
                    }
                }
            }
        }
    }
}

typedef CUresult (*PFN_encodeTiled)(CUtensorMap*, CUtensorMapDataType, cuuint32_t, void*, const cuuint64_t*, const cuuint64_t*,
                                    const cuuint32_t*, const cuuint32_t*, CUtensorMapInterleave, CUtensorMapSwizzle,
                                    CUtensorMapL2promotion, CUtensorMapFloatOOBfill);

static CUtensorMap make_map(PFN_encodeTiled enc, const void* ptr, int rank, const cuuint64_t* dims, const cuuint64_t* strides, const cuuint32_t* box,
                            CUtensorMapSwizzle sw = CU_TENSOR_MAP_SWIZZLE_128B, CUtensorMapDataType dt = CU_TENSOR_MAP_DATA_TYPE_BFLOAT16) {
    CUtensorMap m;
    cuuint32_t es[5] = {1, 1, 1, 1, 1};
    enc(&m, dt, rank, (void*)ptr, dims, strides, box, es, CU_TENSOR_MAP_INTERLEAVE_NONE,
        sw, CU_TENSOR_MAP_L2_PROMOTION_L2_128B, CU_TENSOR_MAP_FLOAT_OOB_FILL_NONE);
    return m;
}

extern "C" void kernel_launch(void* const* d_in, const int* in_sizes, int n_in, void* d_out, int out_size) {
    const bf16* x = (const bf16*)d_in[0];
    const bf16* wr = (const bf16*)d_in[1];
    const bf16* wi = (const bf16*)d_in[2];
    const bf16* Bre = (const bf16*)d_in[6];
    const bf16* Bim = (const bf16*)d_in[7];
    const bf16* Cre = (const bf16*)d_in[8];
    const bf16* Cim = (const bf16*)d_in[9];

    void* fn = nullptr;
    cudaDriverEntryPointQueryResult st;
    cudaGetDriverEntryPoint("cuTensorMapEncodeTiled", &fn, cudaEnableDefault, &st);
    PFN_encodeTiled enc = (PFN_encodeTiled)fn;
    void *p_hT, *p_U;
    cudaGetSymbolAddress(&p_hT, g_hT);
    cudaGetSymbolAddress(&p_U, g_U);

    Params P;
    P.lam_re = (const bf16*)d_in[4]; P.lam_im = (const bf16*)d_in[5]; P.log_dt = (const bf16*)d_in[10];
    P.dskip = (const bf16*)d_in[11]; P.gate_w = (const bf16*)d_in[12]; P.c_re = Cre; P.c_im = Cim; P.b_re = Bre; P.b_im = Bim; P.x = x;
    P.swapB = Bim < Bre;

    CUtensorMap mB, mX, mCre, mCim, mXs, mU0, mV, mU2, mXe, mO, mWr, mWi, mH;
    {
        cuuint64_t d[4] = {64, 2052, 2, 4}, s[3] = {128, 262656, 525312};
        cuuint32_t bx[4] = {64, 9, 1, 4};
        mWr = make_map(enc, wr, 4, d, s, bx, CU_TENSOR_MAP_SWIZZLE_NONE);
        mWi = make_map(enc, wi, 4, d, s, bx, CU_TENSOR_MAP_SWIZZLE_NONE);
    }
    {
        cuuint64_t d[3] = {128, 32, 256}, s[2] = {1024, 32768};
        cuuint32_t bx[3] = {128, 1, 16 / HN};
        mH = make_map(enc, p_hT, 3, d, s, bx, CU_TENSOR_MAP_SWIZZLE_NONE, CU_TENSOR_MAP_DATA_TYPE_UINT64);
    }
    {
        const bf16* lo = P.swapB ? Bim : Bre; const bf16* hi = P.swapB ? Bre : Bim;
        cuuint64_t d[4] = {1024, 8, 2, 128}, s[3] = {2048, (cuuint64_t)((const char*)hi - (const char*)lo), 16384};
        cuuint32_t bx[4] = {64, 8, 2, 8};
        mB = make_map(enc, lo, 4, d, s, bx);
    }
    {
        cuuint64_t d[4] = {1024, 2, 4, 976}, s[3] = {2048, 32 * 2048, 2 * 2048};
        cuuint32_t bx[4] = {64, 2, 4, 16};
        mX = make_map(enc, x, 4, d, s, bx);
    }
    {
        cuuint64_t d[3] = {64, 1024, 16}, s[2] = {2048, 128};
        cuuint32_t bx[3] = {64, 128, 1};
        mCre = make_map(enc, Cre, 3, d, s, bx);
        mCim = make_map(enc, Cim, 3, d, s, bx);
    }
    {
        cuuint64_t d[3] = {64, 256, 128}, s[2] = {16384, 128};
        cuuint32_t bx[3] = {64, 64, 2};
        mV = make_map(enc, p_U, 3, d, s, bx);
    }
    {
        cuuint64_t d[5] = {1024, 8, 2, 16, 8}, s[4] = {16 * 2048, 8 * 2048, 128 * 2048, 2048};
        cuuint32_t bx[5] = {64, 8, 2, 4, 1};
        mXe = make_map(enc, x, 5, d, s, bx);
    }
    {
        cuuint64_t d[3] = {1024, 256, 8}, s[2] = {8 * 4096, 4096};
        cuuint32_t bx[3] = {32, 16, 1};
        mO = make_map(enc, d_out, 3, d, s, bx, CU_TENSOR_MAP_SWIZZLE_128B, CU_TENSOR_MAP_DATA_TYPE_FLOAT32);
    }
    {
        cuuint64_t d[4] = {1024, 64, 4, 8}, s[3] = {32 * 2048, 8 * 2048, 2048};
        cuuint32_t bx[4] = {64, 64, 1, 1};
        mXs = make_map(enc, x, 4, d, s, bx);
    }
    {
        cuuint64_t d[4] = {1024, 128, 2, 8}, s[3] = {32768, 16384, 2048};
        cuuint32_t bx[4] = {64, 32, 2, 1};
        mU0 = make_map(enc, p_U, 4, d, s, bx);
    }
    {
        cuuint64_t d[4] = {64, 8, 16, 256}, s[3] = {2048, 128, 16384};
        cuuint32_t bx[4] = {64, 8, 4, 1};
        mU2 = make_map(enc, p_U, 4, d, s, bx);
    }
    cudaFuncSetAttribute(fused_kernel, cudaFuncAttributeMaxDynamicSharedMemorySize, SMEM_BYTES);
    fused_kernel<<<130, 384, SMEM_BYTES, cudaStreamPerThread>>>(mB, mX, mXs, mU0, mU2, mXe, mCre, mCim, mV, mO, mWr, mWi, mH, P);
}
```

```cpp
#include <cuda_runtime.h>
#include <cuda_bf16.h>
#include <cuda.h>
#include <stdint.h>

typedef __nv_bfloat16 bf16;

__device__ const __align__(128) uint32_t c_tab[11264] = {
0x3f803f80,0xbf803f80,0x3f803f80,0xbf803f80,0x3f803f80,0xbf803f80,0x3f803f80,0xbf803f80,0x3f803f80,0xbf803f80,0x3f803f80,0xbf803f80,
0x3f803f80,0xbf803f80,0x3f803f80,0xbf803f80,0x3f7f3f80,0xbdc98000,0x3f223f35,0xbf46bf35,0x3f753f7b,0xbe95be48,0x3ef13f0e,0xbf62bf55,
0x3f623f6d,0xbef1bec4,0x3e953ec4,0xbf75bf6d,0x3f463f55,0xbf22bf0e,0x3dc93e48,0xbf7fbf7b,0x3f7b3f80,0xbe488000,0xbe480000,0xbf7bbf80,
0x3f553f6d,0xbf0ebec4,0xbf0ebec4,0xbf55bf6d,0x3f0e3f35,0xbf55bf35,0xbf55bf35,0xbf0ebf35,0x3e483ec4,0xbf7bbf6d,0xbf7bbf6d,0xbe48bec4,
0x3f753f80,0xbe958000,0xbf62bf35,0xbef1bf35,0x3f223f55,0xbf46bf0e,0xbf7fbf7b,0x3dc9be48,0x3dc93ec4,0xbf7fbf6d,0xbf46bf6d,0x3f223ec4,
0xbef1be48,0xbf62bf7b,0xbe95bf0e,0x3f753f55,0x3f6d3f80,0xbec48000,0xbf6dbf80,0x3ec48000,0x3ec43f35,0xbf6dbf35,0xbec4bf35,0x3f6d3f35,
0xbec40000,0xbf6dbf80,0x3ec40000,0x3f6d3f80,0xbf6dbf35,0xbec4bf35,0x3f6d3f35,0x3ec43f35,0x3f623f80,0xbef18000,0xbe95bf35,0x3f753f35,
0x3dc93f0e,0xbf7fbf55,0x3f223e48,0x3f463f7b,0xbf46bec4,0xbf22bf6d,0x3f7f3f6d,0xbdc93ec4,0xbf75bf7b,0x3e95be48,0x3ef13f55,0xbf62bf0e,
0x3f553f80,0xbf0e8000,0x3f0e0000,0x3f553f80,0xbe483ec4,0xbf7bbf6d,0x3f7b3f6d,0xbe483ec4,0xbf7bbf35,0xbe48bf35,0x3e483f35,0xbf7bbf35,
0xbf0ebf6d,0x3f553ec4,0xbf55bec4,0xbf0ebf6d,0x3f463f80,0xbf228000,0x3f7f3f35,0x3dc93f35,0xbef13e48,0xbf62bf7b,0x3e953f55,0xbf75bf0e,
0xbf75bf6d,0x3e95bec4,0xbf62bec4,0xbef1bf6d,0x3dc9bf0e,0x3f7f3f55,0xbf22bf7b,0x3f463e48,0x3f353f80,0xbf358000,0x3f353f80,0xbf358000,
0xbf350000,0xbf35bf80,0xbf350000,0xbf35bf80,0xbf35bf80,0x3f358000,0xbf35bf80,0x3f358000,0x3f350000,0x3f353f80,0x3f350000,0x3f353f80,
0x3f223f80,0xbf468000,0xbdc93f35,0xbf7fbf35,0xbf62be48,0xbef1bf7b,0xbf75bf55,0x3e95bf0e,0xbe95bf6d,0x3f753ec4,0x3ef1bec4,0x3f623f6d,
0x3f7f3f0e,0x3dc93f55,0x3f463f7b,0xbf223e48,0x3f0e3f80,0xbf558000,0xbf550000,0xbf0ebf80,0xbf7bbec4,0xbe48bf6d,0xbe48bf6d,0x3f7b3ec4,
0x3e48bf35,0x3f7b3f35,0x3f7b3f35,0xbe483f35,0x3f553f6d,0xbf0e3ec4,0xbf0e3ec4,0xbf55bf6d,0x3ef13f80,0xbf628000,0xbf75bf35,0x3e95bf35,
0xbf7fbf0e,0x3dc9bf55,0x3f46be48,0x3f223f7b,0x3f22bec4,0x3f463f6d,0x3dc93f6d,0xbf7fbec4,0x3e953f7b,0xbf75be48,0xbf62bf55,0x3ef1bf0e,
0x3ec43f80,0xbf6d8000,0xbec4bf80,0x3f6d8000,0xbf6dbf35,0x3ec4bf35,0x3f6d3f35,0xbec43f35,0x3f6d0000,0x3ec43f80,0xbf6d0000,0xbec4bf80,
0xbec43f35,0xbf6dbf35,0x3ec4bf35,0x3f6d3f35,0x3e953f80,0xbf758000,0x3ef1bf35,0x3f623f35,0xbf46bf55,0x3f22bf0e,0x3dc93f7b,0xbf7fbe48,
0x3f7f3ec4,0xbdc93f6d,0xbf22bf6d,0x3f46bec4,0xbf623e48,0xbef1bf7b,0x3f753f0e,0xbe953f55,0x3e483f80,0xbf7b8000,0x3f7b0000,0x3e483f80,
0xbf0ebf6d,0x3f55bec4,0xbf553ec4,0xbf0ebf6d,0x3f553f35,0xbf0e3f35,0x3f0ebf35,0x3f553f35,0xbf7bbec4,0x3e48bf6d,0xbe483f6d,0xbf7bbec4,
0x3dc93f80,0xbf7f8000,0x3f463f35,0xbf223f35,0xbe95bf7b,0x3f75be48,0xbf62bf0e,0x3ef1bf55,0x3ef13f6d,0xbf623ec4,0x3f753ec4,0xbe953f6d,
0xbf22bf55,0x3f46bf0e,0xbf7fbe48,0x3dc9bf7b,0x3f80,0xbf808000,0x3f80,0xbf808000,0xbf80,0x3f808000,0xbf80,0x3f808000,
0x3f80,0xbf808000,0x3f80,0xbf808000,0xbf80,0x3f808000,0xbf80,0x3f808000,0xbdc93f80,0xbf7f8000,0xbf463f35,0xbf22bf35,
0x3e95bf7b,0x3f753e48,0x3f62bf0e,0x3ef13f55,0xbef13f6d,0xbf62bec4,0xbf753ec4,0xbe95bf6d,0x3f22bf55,0x3f463f0e,0x3f7fbe48,0x3dc93f7b,
0xbe483f80,0xbf7b8000,0xbf7b0000,0x3e48bf80,0x3f0ebf6d,0x3f553ec4,0x3f553ec4,0xbf0e3f6d,0xbf553f35,0xbf0ebf35,0xbf0ebf35,0x3f55bf35,
0x3f7bbec4,0x3e483f6d,0x3e483f6d,0xbf7b3ec4,0xbe953f80,0xbf758000,0xbef1bf35,0x3f62bf35,0x3f46bf55,0x3f223f0e,0xbdc93f7b,0xbf7f3e48,
0xbf7f3ec4,0xbdc9bf6d,0x3f22bf6d,0x3f463ec4,0x3f623e48,0xbef13f7b,0xbf753f0e,0xbe95bf55,0xbec43f80,0xbf6d8000,0x3ec4bf80,0x3f6d8000,
0x3f6dbf35,0x3ec43f35,0xbf6d3f35,0xbec4bf35,0xbf6d0000,0x3ec4bf80,0x3f6d0000,0xbec43f80,0x3ec43f35,0xbf6d3f35,0xbec4bf35,0x3f6dbf35,
0xbef13f80,0xbf628000,0x3f75bf35,0x3e953f35,0x3f7fbf0e,0x3dc93f55,0xbf46be48,0x3f22bf7b,0xbf22bec4,0x3f46bf6d,0xbdc93f6d,0xbf7f3ec4,
0xbe953f7b,0xbf753e48,0x3f62bf55,0x3ef13f0e,0xbf0e3f80,0xbf558000,0x3f550000,0xbf0e3f80,0x3f7bbec4,0xbe483f6d,0x3e48bf6d,0x3f7bbec4,
0xbe48bf35,0x3f7bbf35,0xbf7b3f35,0xbe48bf35,0xbf553f6d,0xbf0ebec4,0x3f0e3ec4,0xbf553f6d,0xbf223f80,0xbf468000,0x3dc93f35,0xbf7f3f35,
0x3f62be48,0xbef13f7b,0x3f75bf55,0x3e953f0e,0x3e95bf6d,0x3f75bec4,0xbef1bec4,0x3f62bf6d,0xbf7f3f0e,0x3dc9bf55,0xbf463f7b,0xbf22be48,
0xbf353f80,0xbf358000,0xbf353f80,0xbf358000,0x3f350000,0xbf353f80,0x3f350000,0xbf353f80,0x3f35bf80,0x3f358000,0x3f35bf80,0x3f358000,
0xbf350000,0x3f35bf80,0xbf350000,0x3f35bf80,0xbf463f80,0xbf228000,0xbf7f3f35,0x3dc9bf35,0x3ef13e48,0xbf623f7b,0xbe953f55,0xbf753f0e,
0x3f75bf6d,0x3e953ec4,0x3f62bec4,0xbef13f6d,0xbdc9bf0e,0x3f7fbf55,0x3f22bf7b,0x3f46be48,0xbf553f80,0xbf0e8000,0xbf0e0000,0x3f55bf80,
0x3e483ec4,0xbf7b3f6d,0xbf7b3f6d,0xbe48bec4,0x3f7bbf35,0xbe483f35,0xbe483f35,0xbf7b3f35,0x3f0ebf6d,0x3f55bec4,0x3f55bec4,0xbf0e3f6d,
0xbf623f80,0xbef18000,0x3e95bf35,0x3f75bf35,0xbdc93f0e,0xbf7f3f55,0xbf223e48,0x3f46bf7b,0x3f46bec4,0xbf223f6d,0xbf7f3f6d,0xbdc9bec4,
0x3f75bf7b,0x3e953e48,0xbef13f55,0xbf623f0e,0xbf6d3f80,0xbec48000,0x3f6dbf80,0x3ec48000,0xbec43f35,0xbf6d3f35,0x3ec4bf35,0x3f6dbf35,
0x3ec40000,0xbf6d3f80,0xbec40000,0x3f6dbf80,0x3f6dbf35,0xbec43f35,0xbf6d3f35,0x3ec4bf35,0xbf753f80,0xbe958000,0x3f62bf35,0xbef13f35,
0xbf223f55,0xbf463f0e,0x3f7fbf7b,0x3dc93e48,0xbdc93ec4,0xbf7f3f6d,0x3f46bf6d,0x3f22bec4,0x3ef1be48,0xbf623f7b,0x3e95bf0e,0x3f75bf55,
0xbf7b3f80,0xbe488000,0x3e480000,0xbf7b3f80,0xbf553f6d,0xbf0e3ec4,0x3f0ebec4,0xbf553f6d,0xbf0e3f35,0xbf553f35,0x3f55bf35,0xbf0e3f35,
0xbe483ec4,0xbf7b3f6d,0x3f7bbf6d,0xbe483ec4,0xbf7f3f80,0xbdc98000,0xbf223f35,0xbf463f35,0xbf753f7b,0xbe953e48,0xbef13f0e,0xbf623f55,
0xbf623f6d,0xbef13ec4,0xbe953ec4,0xbf753f6d,0xbf463f55,0xbf223f0e,0xbdc93e48,0xbf7f3f7b,0x3f803f80,0xbf803f80,0x3f803f80,0xbf803f80,
0x3f803f80,0xbf803f80,0x3f803f80,0xbf803f80,0x3f803f80,0xbf803f80,0x3f803f80,0xbf803f80,0x3f803f80,0xbf803f80,0x3f803f80,0xbf803f80,
0xbdc90000,0xbf7fbf80,0xbf46bf35,0xbf22bf35,0xbe95be48,0xbf75bf7b,0xbf62bf55,0xbef1bf0e,0xbef1bec4,0xbf62bf6d,0xbf75bf6d,0xbe95bec4,
0xbf22bf0e,0xbf46bf55,0xbf7fbf7b,0xbdc9be48,0xbf7bbf80,0x3e488000,0x3e480000,0x3f7b3f80,0xbf55bf6d,0x3f0e3ec4,0x3f0e3ec4,0x3f553f6d,
0xbf0ebf35,0x3f553f35,0x3f553f35,0x3f0e3f35,0xbe48bec4,0x3f7b3f6d,0x3f7b3f6d,0x3e483ec4,0x3e950000,0x3f753f80,0x3ef13f35,0xbf62bf35,
0x3f463f0e,0x3f223f55,0xbdc93e48,0xbf7fbf7b,0x3f7f3f6d,0x3dc93ec4,0xbf22bec4,0xbf46bf6d,0x3f623f7b,0xbef1be48,0xbf75bf55,0xbe95bf0e,
0x3f6d3f80,0xbec48000,0xbf6dbf80,0x3ec48000,0x3ec43f35,0xbf6dbf35,0xbec4bf35,0x3f6d3f35,0xbec40000,0xbf6dbf80,0x3ec40000,0x3f6d3f80,
0xbf6dbf35,0xbec4bf35,0x3f6d3f35,0x3ec43f35,0xbef10000,0xbf62bf80,0x3f753f35,0x3e953f35,0xbf7fbf55,0xbdc9bf0e,0x3f463f7b,0xbf22be48,
0xbf22bf6d,0x3f463ec4,0xbdc93ec4,0xbf7fbf6d,0x3e95be48,0x3f753f7b,0xbf62bf0e,0xbef1bf55,0xbf55bf80,0x3f0e8000,0xbf0e0000,0xbf55bf80,
0x3e48bec4,0x3f7b3f6d,0xbf7bbf6d,0x3e48bec4,0x3f7b3f35,0x3e483f35,0xbe48bf35,0x3f7b3f35,0x3f0e3f6d,0xbf55bec4,0x3f553ec4,0x3f0e3f6d,
0x3f220000,0x3f463f80,0xbdc9bf35,0x3f7f3f35,0x3f623f7b,0xbef13e48,0x3f753f0e,0x3e953f55,0xbe953ec4,0xbf75bf6d,0x3ef13f6d,0xbf62bec4,
0xbf7fbf55,0x3dc9bf0e,0xbf46be48,0xbf22bf7b,0x3f353f80,0xbf358000,0x3f353f80,0xbf358000,0xbf350000,0xbf35bf80,0xbf350000,0xbf35bf80,
0xbf35bf80,0x3f358000,0xbf35bf80,0x3f358000,0x3f350000,0x3f353f80,0x3f350000,0x3f353f80,0xbf460000,0xbf22bf80,0xbf7fbf35,0x3dc9bf35,
0xbef1bf7b,0x3f623e48,0x3e95bf0e,0x3f753f55,0x3f753ec4,0x3e953f6d,0x3f623f6d,0xbef13ec4,0x3dc93f55,0xbf7fbf0e,0xbf223e48,0xbf46bf7b,
0xbf0ebf80,0x3f558000,0x3f550000,0x3f0e3f80,0x3f7b3ec4,0x3e483f6d,0x3e483f6d,0xbf7bbec4,0xbe483f35,0xbf7bbf35,0xbf7bbf35,0x3e48bf35,
0xbf55bf6d,0x3f0ebec4,0x3f0ebec4,0x3f553f6d,0x3f620000,0x3ef13f80,0xbe953f35,0xbf75bf35,0xbdc93f55,0xbf7fbf0e,0xbf22bf7b,0x3f46be48,
0xbf46bf6d,0x3f22bec4,0x3f7f3ec4,0x3dc93f6d,0x3f753e48,0x3e953f7b,0xbef13f0e,0xbf62bf55,0x3ec43f80,0xbf6d8000,0xbec4bf80,0x3f6d8000,
0xbf6dbf35,0x3ec4bf35,0x3f6d3f35,0xbec43f35,0x3f6d0000,0x3ec43f80,0xbf6d0000,0xbec4bf80,0xbec43f35,0xbf6dbf35,0x3ec4bf35,0x3f6d3f35,
0xbf750000,0xbe95bf80,0x3f623f35,0xbef13f35,0x3f22bf0e,0x3f463f55,0xbf7fbe48,0xbdc9bf7b,0xbdc93f6d,0xbf7fbec4,0x3f46bec4,0x3f223f6d,
0xbef1bf7b,0x3f62be48,0xbe953f55,0xbf75bf0e,0xbe48bf80,0x3f7b8000,0xbf7b0000,0xbe48bf80,0x3f0e3f6d,0xbf553ec4,0x3f55bec4,0x3f0e3f6d,
0xbf55bf35,0x3f0ebf35,0xbf0e3f35,0xbf55bf35,0x3f7b3ec4,0xbe483f6d,0x3e48bf6d,0x3f7b3ec4,0x3f7f0000,0x3dc93f80,0x3f22bf35,0x3f463f35,
0xbf753e48,0xbe95bf7b,0xbef13f55,0xbf62bf0e,0x3f62bec4,0x3ef13f6d,0x3e95bf6d,0x3f753ec4,0xbf463f0e,0xbf22bf55,0xbdc93f7b,0xbf7fbe48,
0x3f80,0xbf808000,0x3f80,0xbf808000,0xbf80,0x3f808000,0xbf80,0x3f808000,0x3f80,0xbf808000,0x3f80,0xbf808000,
0xbf80,0x3f808000,0xbf80,0x3f808000,0xbf7f0000,0x3dc9bf80,0xbf22bf35,0x3f46bf35,0x3f753e48,0xbe953f7b,0x3ef13f55,0xbf623f0e,
0xbf62bec4,0x3ef1bf6d,0xbe95bf6d,0x3f75bec4,0x3f463f0e,0xbf223f55,0x3dc93f7b,0xbf7f3e48,0x3e48bf80,0x3f7b8000,0x3f7b0000,0xbe483f80,
0xbf0e3f6d,0xbf55bec4,0xbf55bec4,0x3f0ebf6d,0x3f55bf35,0x3f0e3f35,0x3f0e3f35,0xbf553f35,0xbf7b3ec4,0xbe48bf6d,0xbe48bf6d,0x3f7bbec4,
0x3f750000,0xbe953f80,0xbf623f35,0xbef1bf35,0xbf22bf0e,0x3f46bf55,0x3f7fbe48,0xbdc93f7b,0x3dc93f6d,0xbf7f3ec4,0xbf46bec4,0x3f22bf6d,
0x3ef1bf7b,0x3f623e48,0x3e953f55,0xbf753f0e,0xbec43f80,0xbf6d8000,0x3ec4bf80,0x3f6d8000,0x3f6dbf35,0x3ec43f35,0xbf6d3f35,0xbec4bf35,
0xbf6d0000,0x3ec4bf80,0x3f6d0000,0xbec43f80,0x3ec43f35,0xbf6d3f35,0xbec4bf35,0x3f6dbf35,0xbf620000,0x3ef1bf80,0x3e953f35,0xbf753f35,
0x3dc93f55,0xbf7f3f0e,0x3f22bf7b,0x3f463e48,0x3f46bf6d,0x3f223ec4,0xbf7f3ec4,0x3dc9bf6d,0xbf753e48,0x3e95bf7b,0x3ef13f0e,0xbf623f55,
0x3f0ebf80,0x3f558000,0xbf550000,0x3f0ebf80,0xbf7b3ec4,0x3e48bf6d,0xbe483f6d,0xbf7b3ec4,0x3e483f35,0xbf7b3f35,0x3f7bbf35,0x3e483f35,
0x3f55bf6d,0x3f0e3ec4,0xbf0ebec4,0x3f55bf6d,0x3f460000,0xbf223f80,0x3f7fbf35,0x3dc93f35,0x3ef1bf7b,0x3f62be48,0xbe95bf0e,0x3f75bf55,
0xbf753ec4,0x3e95bf6d,0xbf623f6d,0xbef1bec4,0xbdc93f55,0xbf7f3f0e,0x3f223e48,0xbf463f7b,0xbf353f80,0xbf358000,0xbf353f80,0xbf358000,
0x3f350000,0xbf353f80,0x3f350000,0xbf353f80,0x3f35bf80,0x3f358000,0x3f35bf80,0x3f358000,0xbf350000,0x3f35bf80,0xbf350000,0x3f35bf80,
0xbf220000,0x3f46bf80,0x3dc9bf35,0x3f7fbf35,0xbf623f7b,0xbef1be48,0xbf753f0e,0x3e95bf55,0x3e953ec4,0xbf753f6d,0xbef13f6d,0xbf623ec4,
0x3f7fbf55,0x3dc93f0e,0x3f46be48,0xbf223f7b,0x3f55bf80,0x3f0e8000,0x3f0e0000,0xbf553f80,0xbe48bec4,0x3f7bbf6d,0x3f7bbf6d,0x3e483ec4,
0xbf7b3f35,0x3e48bf35,0x3e48bf35,0x3f7bbf35,0xbf0e3f6d,0xbf553ec4,0xbf553ec4,0x3f0ebf6d,0x3ef10000,0xbf623f80,0xbf753f35,0x3e95bf35,
0x3f7fbf55,0xbdc93f0e,0xbf463f7b,0xbf223e48,0x3f22bf6d,0x3f46bec4,0x3dc93ec4,0xbf7f3f6d,0xbe95be48,0x3f75bf7b,0x3f62bf0e,0xbef13f55,
0xbf6d3f80,0xbec48000,0x3f6dbf80,0x3ec48000,0xbec43f35,0xbf6d3f35,0x3ec4bf35,0x3f6dbf35,0x3ec40000,0xbf6d3f80,0xbec40000,0x3f6dbf80,
0x3f6dbf35,0xbec43f35,0xbf6d3f35,0x3ec4bf35,0xbe950000,0x3f75bf80,0xbef13f35,0xbf623f35,0xbf463f0e,0x3f22bf55,0x3dc93e48,0xbf7f3f7b,
0xbf7f3f6d,0x3dc9bec4,0x3f22bec4,0xbf463f6d,0xbf623f7b,0xbef13e48,0x3f75bf55,0xbe953f0e,0x3f7bbf80,0x3e488000,0xbe480000,0x3f7bbf80,
0x3f55bf6d,0x3f0ebec4,0xbf0e3ec4,0x3f55bf6d,0x3f0ebf35,0x3f55bf35,0xbf553f35,0x3f0ebf35,0x3e48bec4,0x3f7bbf6d,0xbf7b3f6d,0x3e48bec4,
0x3dc90000,0xbf7f3f80,0x3f46bf35,0xbf223f35,0x3e95be48,0xbf753f7b,0x3f62bf55,0xbef13f0e,0x3ef1bec4,0xbf623f6d,0x3f75bf6d,0xbe953ec4,
0x3f22bf0e,0xbf463f55,0x3f7fbf7b,0xbdc93e48,0x3f803f80,0xbf803f80,0x3f803f80,0xbf803f80,0x3f803f80,0xbf803f80,0x3f803f80,0xbf803f80,
0x3f803f80,0xbf803f80,0x3f803f80,0xbf803f80,0x3f803f80,0xbf803f80,0x3f803f80,0xbf803f80,0xbf7fbf80,0x3dc98000,0xbf22bf35,0x3f463f35,
0xbf75bf7b,0x3e953e48,0xbef1bf0e,0x3f623f55,0xbf62bf6d,0x3ef13ec4,0xbe95bec4,0x3f753f6d,0xbf46bf55,0x3f223f0e,0xbdc9be48,0x3f7f3f7b,
0x3f7b3f80,0xbe488000,0xbe480000,0xbf7bbf80,0x3f553f6d,0xbf0ebec4,0xbf0ebec4,0xbf55bf6d,0x3f0e3f35,0xbf55bf35,0xbf55bf35,0xbf0ebf35,
0x3e483ec4,0xbf7bbf6d,0xbf7bbf6d,0xbe48bec4,0xbf75bf80,0x3e958000,0x3f623f35,0x3ef13f35,0xbf22bf55,0x3f463f0e,0x3f7f3f7b,0xbdc93e48,
0xbdc9bec4,0x3f7f3f6d,0x3f463f6d,0xbf22bec4,0x3ef13e48,0x3f623f7b,0x3e953f0e,0xbf75bf55,0x3f6d3f80,0xbec48000,0xbf6dbf80,0x3ec48000,
0x3ec43f35,0xbf6dbf35,0xbec4bf35,0x3f6d3f35,0xbec40000,0xbf6dbf80,0x3ec40000,0x3f6d3f80,0xbf6dbf35,0xbec4bf35,0x3f6d3f35,0x3ec43f35,
0xbf62bf80,0x3ef18000,0x3e953f35,0xbf75bf35,0xbdc9bf0e,0x3f7f3f55,0xbf22be48,0xbf46bf7b,0x3f463ec4,0x3f223f6d,0xbf7fbf6d,0x3dc9bec4,
0x3f753f7b,0xbe953e48,0xbef1bf55,0x3f623f0e,0x3f553f80,0xbf0e8000,0x3f0e0000,0x3f553f80,0xbe483ec4,0xbf7bbf6d,0x3f7b3f6d,0xbe483ec4,
0xbf7bbf35,0xbe48bf35,0x3e483f35,0xbf7bbf35,0xbf0ebf6d,0x3f553ec4,0xbf55bec4,0xbf0ebf6d,0xbf46bf80,0x3f228000,0xbf7fbf35,0xbdc9bf35,
0x3ef1be48,0x3f623f7b,0xbe95bf55,0x3f753f0e,0x3f753f6d,0xbe953ec4,0x3f623ec4,0x3ef13f6d,0xbdc93f0e,0xbf7fbf55,0x3f223f7b,0xbf46be48,
0x3f353f80,0xbf358000,0x3f353f80,0xbf358000,0xbf350000,0xbf35bf80,0xbf350000,0xbf35bf80,0xbf35bf80,0x3f358000,0xbf35bf80,0x3f358000,
0x3f350000,0x3f353f80,0x3f350000,0x3f353f80,0xbf22bf80,0x3f468000,0x3dc9bf35,0x3f7f3f35,0x3f623e48,0x3ef13f7b,0x3f753f55,0xbe953f0e,
0x3e953f6d,0xbf75bec4,0xbef13ec4,0xbf62bf6d,0xbf7fbf0e,0xbdc9bf55,0xbf46bf7b,0x3f22be48,0x3f0e3f80,0xbf558000,0xbf550000,0xbf0ebf80,
0xbf7bbec4,0xbe48bf6d,0xbe48bf6d,0x3f7b3ec4,0x3e48bf35,0x3f7b3f35,0x3f7b3f35,0xbe483f35,0x3f553f6d,0xbf0e3ec4,0xbf0e3ec4,0xbf55bf6d,
0xbef1bf80,0x3f628000,0x3f753f35,0xbe953f35,0x3f7f3f0e,0xbdc93f55,0xbf463e48,0xbf22bf7b,0xbf223ec4,0xbf46bf6d,0xbdc9bf6d,0x3f7f3ec4,
0xbe95bf7b,0x3f753e48,0x3f623f55,0xbef13f0e,0x3ec43f80,0xbf6d8000,0xbec4bf80,0x3f6d8000,0xbf6dbf35,0x3ec4bf35,0x3f6d3f35,0xbec43f35,
0x3f6d0000,0x3ec43f80,0xbf6d0000,0xbec4bf80,0xbec43f35,0xbf6dbf35,0x3ec4bf35,0x3f6d3f35,0xbe95bf80,0x3f758000,0xbef13f35,0xbf62bf35,
0x3f463f55,0xbf223f0e,0xbdc9bf7b,0x3f7f3e48,0xbf7fbec4,0x3dc9bf6d,0x3f223f6d,0xbf463ec4,0x3f62be48,0x3ef13f7b,0xbf75bf0e,0x3e95bf55,
0x3e483f80,0xbf7b8000,0x3f7b0000,0x3e483f80,0xbf0ebf6d,0x3f55bec4,0xbf553ec4,0xbf0ebf6d,0x3f553f35,0xbf0e3f35,0x3f0ebf35,0x3f553f35,
0xbf7bbec4,0x3e48bf6d,0xbe483f6d,0xbf7bbec4,0xbdc9bf80,0x3f7f8000,0xbf46bf35,0x3f22bf35,0x3e953f7b,0xbf753e48,0x3f623f0e,0xbef13f55,
0xbef1bf6d,0x3f62bec4,0xbf75bec4,0x3e95bf6d,0x3f223f55,0xbf463f0e,0x3f7f3e48,0xbdc93f7b,0x3f80,0xbf808000,0x3f80,0xbf808000,
0xbf80,0x3f808000,0xbf80,0x3f808000,0x3f80,0xbf808000,0x3f80,0xbf808000,0xbf80,0x3f808000,0xbf80,0x3f808000,
0x3dc9bf80,0x3f7f8000,0x3f46bf35,0x3f223f35,0xbe953f7b,0xbf75be48,0xbf623f0e,0xbef1bf55,0x3ef1bf6d,0x3f623ec4,0x3f75bec4,0x3e953f6d,
0xbf223f55,0xbf46bf0e,0xbf7f3e48,0xbdc9bf7b,0xbe483f80,0xbf7b8000,0xbf7b0000,0x3e48bf80,0x3f0ebf6d,0x3f553ec4,0x3f553ec4,0xbf0e3f6d,
0xbf553f35,0xbf0ebf35,0xbf0ebf35,0x3f55bf35,0x3f7bbec4,0x3e483f6d,0x3e483f6d,0xbf7b3ec4,0x3e95bf80,0x3f758000,0x3ef13f35,0xbf623f35,
0xbf463f55,0xbf22bf0e,0x3dc9bf7b,0x3f7fbe48,0x3f7fbec4,0x3dc93f6d,0xbf223f6d,0xbf46bec4,0xbf62be48,0x3ef1bf7b,0x3f75bf0e,0x3e953f55,
0xbec43f80,0xbf6d8000,0x3ec4bf80,0x3f6d8000,0x3f6dbf35,0x3ec43f35,0xbf6d3f35,0xbec4bf35,0xbf6d0000,0x3ec4bf80,0x3f6d0000,0xbec43f80,
0x3ec43f35,0xbf6d3f35,0xbec4bf35,0x3f6dbf35,0x3ef1bf80,0x3f628000,0xbf753f35,0xbe95bf35,0xbf7f3f0e,0xbdc9bf55,0x3f463e48,0xbf223f7b,
0x3f223ec4,0xbf463f6d,0x3dc9bf6d,0x3f7fbec4,0x3e95bf7b,0x3f75be48,0xbf623f55,0xbef1bf0e,0xbf0e3f80,0xbf558000,0x3f550000,0xbf0e3f80,
0x3f7bbec4,0xbe483f6d,0x3e48bf6d,0x3f7bbec4,0xbe48bf35,0x3f7bbf35,0xbf7b3f35,0xbe48bf35,0xbf553f6d,0xbf0ebec4,0x3f0e3ec4,0xbf553f6d,
0x3f22bf80,0x3f468000,0xbdc9bf35,0x3f7fbf35,0xbf623e48,0x3ef1bf7b,0xbf753f55,0xbe95bf0e,0xbe953f6d,0xbf753ec4,0x3ef13ec4,0xbf623f6d,
0x3f7fbf0e,0xbdc93f55,0x3f46bf7b,0x3f223e48,0xbf353f80,0xbf358000,0xbf353f80,0xbf358000,0x3f350000,0xbf353f80,0x3f350000,0xbf353f80,
0x3f35bf80,0x3f358000,0x3f35bf80,0x3f358000,0xbf350000,0x3f35bf80,0xbf350000,0x3f35bf80,0x3f46bf80,0x3f228000,0x3f7fbf35,0xbdc93f35,
0xbef1be48,0x3f62bf7b,0x3e95bf55,0x3f75bf0e,0xbf753f6d,0xbe95bec4,0xbf623ec4,0x3ef1bf6d,0x3dc93f0e,0xbf7f3f55,0xbf223f7b,0xbf463e48,
0xbf553f80,0xbf0e8000,0xbf0e0000,0x3f55bf80,0x3e483ec4,0xbf7b3f6d,0xbf7b3f6d,0xbe48bec4,0x3f7bbf35,0xbe483f35,0xbe483f35,0xbf7b3f35,
0x3f0ebf6d,0x3f55bec4,0x3f55bec4,0xbf0e3f6d,0x3f62bf80,0x3ef18000,0xbe953f35,0xbf753f35,0x3dc9bf0e,0x3f7fbf55,0x3f22be48,0xbf463f7b,
0xbf463ec4,0x3f22bf6d,0x3f7fbf6d,0x3dc93ec4,0xbf753f7b,0xbe95be48,0x3ef1bf55,0x3f62bf0e,0xbf6d3f80,0xbec48000,0x3f6dbf80,0x3ec48000,
0xbec43f35,0xbf6d3f35,0x3ec4bf35,0x3f6dbf35,0x3ec40000,0xbf6d3f80,0xbec40000,0x3f6dbf80,0x3f6dbf35,0xbec43f35,0xbf6d3f35,0x3ec4bf35,
0x3f75bf80,0x3e958000,0xbf623f35,0x3ef1bf35,0x3f22bf55,0x3f46bf0e,0xbf7f3f7b,0xbdc9be48,0x3dc9bec4,0x3f7fbf6d,0xbf463f6d,0xbf223ec4,
0xbef13e48,0x3f62bf7b,0xbe953f0e,0xbf753f55,0xbf7b3f80,0xbe488000,0x3e480000,0xbf7b3f80,0xbf553f6d,0xbf0e3ec4,0x3f0ebec4,0xbf553f6d,
0xbf0e3f35,0xbf553f35,0x3f55bf35,0xbf0e3f35,0xbe483ec4,0xbf7b3f6d,0x3f7bbf6d,0xbe483ec4,0x3f7fbf80,0x3dc98000,0x3f22bf35,0x3f46bf35,
0x3f75bf7b,0x3e95be48,0x3ef1bf0e,0x3f62bf55,0x3f62bf6d,0x3ef1bec4,0x3e95bec4,0x3f75bf6d,0x3f46bf55,0x3f22bf0e,0x3dc9be48,0x3f7fbf7b,
0x3f803f80,0xbf803f80,0x3f803f80,0xbf803f80,0x3f803f80,0xbf803f80,0x3f803f80,0xbf803f80,0x3f803f80,0xbf803f80,0x3f803f80,0xbf803f80,
0x3f803f80,0xbf803f80,0x3f803f80,0xbf803f80,0x3dc90000,0x3f7f3f80,0x3f463f35,0x3f223f35,0x3e953e48,0x3f753f7b,0x3f623f55,0x3ef13f0e,
0x3ef13ec4,0x3f623f6d,0x3f753f6d,0x3e953ec4,0x3f223f0e,0x3f463f55,0x3f7f3f7b,0x3dc93e48,0xbf7bbf80,0x3e488000,0x3e480000,0x3f7b3f80,
0xbf55bf6d,0x3f0e3ec4,0x3f0e3ec4,0x3f553f6d,0xbf0ebf35,0x3f553f35,0x3f553f35,0x3f0e3f35,0xbe48bec4,0x3f7b3f6d,0x3f7b3f6d,0x3e483ec4,
0xbe950000,0xbf75bf80,0xbef1bf35,0x3f623f35,0xbf46bf0e,0xbf22bf55,0x3dc9be48,0x3f7f3f7b,0xbf7fbf6d,0xbdc9bec4,0x3f223ec4,0x3f463f6d,
0xbf62bf7b,0x3ef13e48,0x3f753f55,0x3e953f0e,0x3f6d3f80,0xbec48000,0xbf6dbf80,0x3ec48000,0x3ec43f35,0xbf6dbf35,0xbec4bf35,0x3f6d3f35,
0xbec40000,0xbf6dbf80,0x3ec40000,0x3f6d3f80,0xbf6dbf35,0xbec4bf35,0x3f6d3f35,0x3ec43f35,0x3ef10000,0x3f623f80,0xbf75bf35,0xbe95bf35,
0x3f7f3f55,0x3dc93f0e,0xbf46bf7b,0x3f223e48,0x3f223f6d,0xbf46bec4,0x3dc9bec4,0x3f7f3f6d,0xbe953e48,0xbf75bf7b,0x3f623f0e,0x3ef13f55,
0xbf55bf80,0x3f0e8000,0xbf0e0000,0xbf55bf80,0x3e48bec4,0x3f7b3f6d,0xbf7bbf6d,0x3e48bec4,0x3f7b3f35,0x3e483f35,0xbe48bf35,0x3f7b3f35,
0x3f0e3f6d,0xbf55bec4,0x3f553ec4,0x3f0e3f6d,0xbf220000,0xbf46bf80,0x3dc93f35,0xbf7fbf35,0xbf62bf7b,0x3ef1be48,0xbf75bf0e,0xbe95bf55,
0x3e95bec4,0x3f753f6d,0xbef1bf6d,0x3f623ec4,0x3f7f3f55,0xbdc93f0e,0x3f463e48,0x3f223f7b,0x3f353f80,0xbf358000,0x3f353f80,0xbf358000,
0xbf350000,0xbf35bf80,0xbf350000,0xbf35bf80,0xbf35bf80,0x3f358000,0xbf35bf80,0x3f358000,0x3f350000,0x3f353f80,0x3f350000,0x3f353f80,
0x3f460000,0x3f223f80,0x3f7f3f35,0xbdc93f35,0x3ef13f7b,0xbf62be48,0xbe953f0e,0xbf75bf55,0xbf75bec4,0xbe95bf6d,0xbf62bf6d,0x3ef1bec4,
0xbdc9bf55,0x3f7f3f0e,0x3f22be48,0x3f463f7b,0xbf0ebf80,0x3f558000,0x3f550000,0x3f0e3f80,0x3f7b3ec4,0x3e483f6d,0x3e483f6d,0xbf7bbec4,
0xbe483f35,0xbf7bbf35,0xbf7bbf35,0x3e48bf35,0xbf55bf6d,0x3f0ebec4,0x3f0ebec4,0x3f553f6d,0xbf620000,0xbef1bf80,0x3e95bf35,0x3f753f35,
0x3dc9bf55,0x3f7f3f0e,0x3f223f7b,0xbf463e48,0x3f463f6d,0xbf223ec4,0xbf7fbec4,0xbdc9bf6d,0xbf75be48,0xbe95bf7b,0x3ef1bf0e,0x3f623f55,
0x3ec43f80,0xbf6d8000,0xbec4bf80,0x3f6d8000,0xbf6dbf35,0x3ec4bf35,0x3f6d3f35,0xbec43f35,0x3f6d0000,0x3ec43f80,0xbf6d0000,0xbec4bf80,
0xbec43f35,0xbf6dbf35,0x3ec4bf35,0x3f6d3f35,0x3f750000,0x3e953f80,0xbf62bf35,0x3ef1bf35,0xbf223f0e,0xbf46bf55,0x3f7f3e48,0x3dc93f7b,
0x3dc9bf6d,0x3f7f3ec4,0xbf463ec4,0xbf22bf6d,0x3ef13f7b,0xbf623e48,0x3e95bf55,0x3f753f0e,0xbe48bf80,0x3f7b8000,0xbf7b0000,0xbe48bf80,
0x3f0e3f6d,0xbf553ec4,0x3f55bec4,0x3f0e3f6d,0xbf55bf35,0x3f0ebf35,0xbf0e3f35,0xbf55bf35,0x3f7b3ec4,0xbe483f6d,0x3e48bf6d,0x3f7b3ec4,
0xbf7f0000,0xbdc9bf80,0xbf223f35,0xbf46bf35,0x3f75be48,0x3e953f7b,0x3ef1bf55,0x3f623f0e,0xbf623ec4,0xbef1bf6d,0xbe953f6d,0xbf75bec4,
0x3f46bf0e,0x3f223f55,0x3dc9bf7b,0x3f7f3e48,0x3f80,0xbf808000,0x3f80,0xbf808000,0xbf80,0x3f808000,0xbf80,0x3f808000,
0x3f80,0xbf808000,0x3f80,0xbf808000,0xbf80,0x3f808000,0xbf80,0x3f808000,0x3f7f0000,0xbdc93f80,0x3f223f35,0xbf463f35,
0xbf75be48,0x3e95bf7b,0xbef1bf55,0x3f62bf0e,0x3f623ec4,0xbef13f6d,0x3e953f6d,0xbf753ec4,0xbf46bf0e,0x3f22bf55,0xbdc9bf7b,0x3f7fbe48,
0x3e48bf80,0x3f7b8000,0x3f7b0000,0xbe483f80,0xbf0e3f6d,0xbf55bec4,0xbf55bec4,0x3f0ebf6d,0x3f55bf35,0x3f0e3f35,0x3f0e3f35,0xbf553f35,
0xbf7b3ec4,0xbe48bf6d,0xbe48bf6d,0x3f7bbec4,0xbf750000,0x3e95bf80,0x3f62bf35,0x3ef13f35,0x3f223f0e,0xbf463f55,0xbf7f3e48,0x3dc9bf7b,
0xbdc9bf6d,0x3f7fbec4,0x3f463ec4,0xbf223f6d,0xbef13f7b,0xbf62be48,0xbe95bf55,0x3f75bf0e,0xbec43f80,0xbf6d8000,0x3ec4bf80,0x3f6d8000,
0x3f6dbf35,0x3ec43f35,0xbf6d3f35,0xbec4bf35,0xbf6d0000,0x3ec4bf80,0x3f6d0000,0xbec43f80,0x3ec43f35,0xbf6d3f35,0xbec4bf35,0x3f6dbf35,
0x3f620000,0xbef13f80,0xbe95bf35,0x3f75bf35,0xbdc9bf55,0x3f7fbf0e,0xbf223f7b,0xbf46be48,0xbf463f6d,0xbf22bec4,0x3f7fbec4,0xbdc93f6d,
0x3f75be48,0xbe953f7b,0xbef1bf0e,0x3f62bf55,0x3f0ebf80,0x3f558000,0xbf550000,0x3f0ebf80,0xbf7b3ec4,0x3e48bf6d,0xbe483f6d,0xbf7b3ec4,
0x3e483f35,0xbf7b3f35,0x3f7bbf35,0x3e483f35,0x3f55bf6d,0x3f0e3ec4,0xbf0ebec4,0x3f55bf6d,0xbf460000,0x3f22bf80,0xbf7f3f35,0xbdc9bf35,
0xbef13f7b,0xbf623e48,0x3e953f0e,0xbf753f55,0x3f75bec4,0xbe953f6d,0x3f62bf6d,0x3ef13ec4,0x3dc9bf55,0x3f7fbf0e,0xbf22be48,0x3f46bf7b,
0xbf353f80,0xbf358000,0xbf353f80,0xbf358000,0x3f350000,0xbf353f80,0x3f350000,0xbf353f80,0x3f35bf80,0x3f358000,0x3f35bf80,0x3f358000,
0xbf350000,0x3f35bf80,0xbf350000,0x3f35bf80,0x3f220000,0xbf463f80,0xbdc93f35,0xbf7f3f35,0x3f62bf7b,0x3ef13e48,0x3f75bf0e,0xbe953f55,
0xbe95bec4,0x3f75bf6d,0x3ef1bf6d,0x3f62bec4,0xbf7f3f55,0xbdc9bf0e,0xbf463e48,0x3f22bf7b,0x3f55bf80,0x3f0e8000,0x3f0e0000,0xbf553f80,
0xbe48bec4,0x3f7bbf6d,0x3f7bbf6d,0x3e483ec4,0xbf7b3f35,0x3e48bf35,0x3e48bf35,0x3f7bbf35,0xbf0e3f6d,0xbf553ec4,0xbf553ec4,0x3f0ebf6d,
0xbef10000,0x3f62bf80,0x3f75bf35,0xbe953f35,0xbf7f3f55,0x3dc9bf0e,0x3f46bf7b,0x3f22be48,0xbf223f6d,0xbf463ec4,0xbdc9bec4,0x3f7fbf6d,
0x3e953e48,0xbf753f7b,0xbf623f0e,0x3ef1bf55,0xbf6d3f80,0xbec48000,0x3f6dbf80,0x3ec48000,0xbec43f35,0xbf6d3f35,0x3ec4bf35,0x3f6dbf35,
0x3ec40000,0xbf6d3f80,0xbec40000,0x3f6dbf80,0x3f6dbf35,0xbec43f35,0xbf6d3f35,0x3ec4bf35,0x3e950000,0xbf753f80,0x3ef1bf35,0x3f62bf35,
0x3f46bf0e,0xbf223f55,0xbdc9be48,0x3f7fbf7b,0x3f7fbf6d,0xbdc93ec4,0xbf223ec4,0x3f46bf6d,0x3f62bf7b,0x3ef1be48,0xbf753f55,0x3e95bf0e,
0x3f7bbf80,0x3e488000,0xbe480000,0x3f7bbf80,0x3f55bf6d,0x3f0ebec4,0xbf0e3ec4,0x3f55bf6d,0x3f0ebf35,0x3f55bf35,0xbf553f35,0x3f0ebf35,
0x3e48bec4,0x3f7bbf6d,0xbf7b3f6d,0x3e48bec4,0xbdc90000,0x3f7fbf80,0xbf463f35,0x3f22bf35,0xbe953e48,0x3f75bf7b,0xbf623f55,0x3ef1bf0e,
0xbef13ec4,0x3f62bf6d,0xbf753f6d,0x3e95bec4,0xbf223f0e,0x3f46bf55,0xbf7f3f7b,0x3dc9be48,0x3f803f80,0xbf353f35,0x3f803f80,0xbf353f35,
0x3f803f80,0xbf353f35,0x3f803f80,0xbf353f35,0x3f803f80,0xbf353f35,0x3f803f80,0xbf353f35,0x3f803f80,0xbf353f35,0x3f803f80,0xbf353f35,
0x3f7e3f80,0xbdfbbcc9,0x3f1d3f31,0xbf4abf39,0x3f733f7a,0xbea1be60,0x3ee63f09,0xbf65bf58,0x3f5f3f6a,0xbefcbecf,0x3e893eb8,0xbf77bf6f,
0x3f423f51,0xbf27bf13,0x3d973e2f,0xbf7fbf7c,0x3f783f80,0xbe79bd49,0xbe79bd49,0xbf78bf80,0x3f4e3f67,0xbf18bedb,0xbf18bedb,0xbf4ebf67,
0x3f043f2c,0xbf5cbf3e,0xbf5cbf3e,0xbf04bf2c,0x3e163eac,0xbf7dbf71,0xbf7dbf71,0xbe16beac,0x3f6f3f7f,0xbeb8bd97,0xbf6abf42,0xbecfbf27,
0x3f133f4a,0xbf51bf1d,0xbf7cbf7e,0x3e2fbdfb,0x3cc93ea1,0xbf80bf73,0xbf39bf65,0x3f313ee6,0xbf09be89,0xbf58bf77,0xbe60befc,0x3f7a3f5f,
0x3f623f7f,0xbef1bdc9,0xbf62bf7f,0x3ef13dc9,0x3e953f22,0xbf75bf46,0xbe95bf22,0x3f753f46,0xbef1bdc9,0xbf62bf7f,0x3ef13dc9,0x3f623f7f,
0xbf75bf46,0xbe95bf22,0x3f753f46,0x3e953f22,0x3f513f7e,0xbf13bdfb,0xbe2fbf1d,0x3f7c3f4a,0xbcc93ee6,0xbf80bf65,0x3f393ea1,0x3f313f73,
0xbf58befc,0xbf09bf5f,0x3f7a3f77,0xbe603e89,0xbf6abf7f,0x3ecfbd97,0x3eb83f42,0xbf6fbf27,0x3f3e3f7d,0xbf2cbe16,0x3f2c3e16,0x3f3e3f7d,
0xbeac3e79,0xbf71bf78,0x3f713f78,0xbeac3e79,0xbf80bf4e,0xbd49bf18,0x3d493f18,0xbf80bf4e,0xbedbbf5c,0x3f673f04,0xbf67bf04,0xbedbbf5c,
0x3f273f7c,0xbf42be2f,0x3f7f3f51,0xbd973f13,0xbf1d3cc9,0xbf4abf80,0x3dfb3f39,0xbf7ebf31,0xbf65bf7a,0x3ee6be60,0xbf73bf09,0xbea1bf58,
0x3e89becf,0x3f773f6a,0xbefcbf6f,0x3f5f3eb8,0x3f0e3f7b,0xbf55be48,0x3f0e3f7b,0xbf55be48,0xbf55be48,0xbf0ebf7b,0xbf55be48,0xbf0ebf7b,
0xbf0ebf7b,0x3f553e48,0xbf0ebf7b,0x3f553e48,0x3f553e48,0x3f0e3f7b,0x3f553e48,0x3f0e3f7b,0x3ee63f7a,0xbf65be60,0xbea13f09,0xbf73bf58,
0xbf77becf,0xbe89bf6a,0xbf5fbf6f,0x3efcbeb8,0xbd97bf51,0x3f7f3f13,0x3f27be2f,0x3f423f7c,0x3f7e3f39,0xbdfb3f31,0x3f1d3f80,0xbf4abcc9,
0x3eac3f78,0xbf71be79,0xbf71be79,0xbeacbf78,0xbf80bf18,0x3d49bf4e,0x3d49bf4e,0x3f803f18,0x3edbbf04,0x3f673f5c,0x3f673f5c,0xbedb3f04,
0x3f2c3f7d,0xbf3e3e16,0xbf3e3e16,0xbf2cbf7d,0x3e603f77,0xbf7abe89,0xbf58bf5f,0x3f09befc,0xbf6fbf42,0x3eb8bf27,0x3f6a3d97,0x3ecf3f7f,
0x3f51bdfb,0x3f133f7e,0xbe2f3f4a,0xbf7cbf1d,0x3cc93f65,0xbf80bee6,0xbf39bf73,0x3f31bea1,0x3dc93f75,0xbf7fbe95,0xbdc9bf75,0x3f7f3e95,
0xbf46bf62,0x3f22bef1,0x3f463f62,0xbf223ef1,0x3f7f3e95,0x3dc93f75,0xbf7fbe95,0xbdc9bf75,0xbf223ef1,0xbf46bf62,0x3f22bef1,0x3f463f62,
0xbcc93f73,0xbf80bea1,0x3f39bee6,0x3f313f65,0xbf09bf77,0x3f58be89,0xbe603f5f,0xbf7abefc,0x3f6a3f27,0xbecf3f42,0xbeb8bf7f,0x3f6fbd97,
0xbf7cbdfb,0xbe2fbf7e,0x3f513f4a,0xbf133f1d,0xbe163f71,0xbf7dbeac,0x3f7d3eac,0xbe163f71,0xbe79bf80,0x3f78bd49,0xbf783d49,0xbe79bf80,
0x3f183f67,0xbf4e3edb,0x3f4ebedb,0x3f183f67,0xbf5cbf2c,0x3f04bf3e,0xbf043f3e,0xbf5cbf2c,0xbe893f6f,0xbf77beb8,0x3efc3f6a,0xbf5f3ecf,
0x3d97bf7c,0x3f7f3e2f,0xbf27bf51,0x3f42bf13,0x3dfb3f80,0xbf7e3cc9,0x3f4a3f31,0xbf1d3f39,0xbea1bf7a,0x3f73be60,0xbf65bf09,0x3ee6bf58,
0xbec43f6d,0xbf6dbec4,0xbec43f6d,0xbf6dbec4,0x3ec4bf6d,0x3f6d3ec4,0x3ec4bf6d,0x3f6d3ec4,0xbec43f6d,0xbf6dbec4,0xbec43f6d,0xbf6dbec4,
0x3ec4bf6d,0x3f6d3ec4,0x3ec4bf6d,0x3f6d3ec4,0xbefc3f6a,0xbf5fbecf,0xbf773eb8,0xbe89bf6f,0x3f27bf51,0x3f423f13,0x3f7fbe2f,0x3d973f7c,
0xbf4a3f31,0xbf1dbf39,0xbf7ebcc9,0x3dfbbf80,0x3f65bf09,0x3ee63f58,0x3f733e60,0xbea13f7a,0xbf183f67,0xbf4ebedb,0xbf4ebedb,0x3f18bf67,
0x3f5cbf2c,0x3f043f3e,0x3f043f3e,0xbf5c3f2c,0xbf7d3eac,0xbe16bf71,0xbe16bf71,0x3f7dbeac,0x3f783d49,0xbe793f80,0xbe793f80,0xbf78bd49,
0xbf313f65,0xbf39bee6,0xbcc9bf73,0x3f80bea1,0x3f7abefc,0x3e603f5f,0xbf093f77,0xbf58be89,0xbf6fbd97,0x3eb8bf7f,0x3f6abf27,0x3ecf3f42,
0x3f133f1d,0xbf513f4a,0xbf7c3dfb,0x3e2fbf7e,0xbf463f62,0xbf22bef1,0x3f46bf62,0x3f223ef1,0x3f7fbe95,0xbdc93f75,0xbf7f3e95,0x3dc9bf75,
0xbf22bef1,0x3f46bf62,0x3f223ef1,0xbf463f62,0xbdc93f75,0xbf7f3e95,0x3dc9bf75,0x3f7fbe95,0xbf583f5f,0xbf09befc,0x3f7abe89,0xbe603f77,
0x3f6abd97,0xbecf3f7f,0xbeb8bf27,0x3f6fbf42,0xbe2fbf4a,0x3f7cbf1d,0xbf133f7e,0xbf51bdfb,0xbf393f73,0xbf31bea1,0x3f80bee6,0xbcc93f65,
0xbf673f5c,0xbedbbf04,0x3edb3f04,0xbf673f5c,0x3f3e3e16,0xbf2c3f7d,0x3f2cbf7d,0x3f3e3e16,0x3eacbf78,0x3f71be79,0xbf713e79,0x3eacbf78,
0xbf803f18,0xbd49bf4e,0x3d493f4e,0xbf803f18,0xbf733f58,0xbea1bf09,0xbee63f7a,0xbf653e60,0x3efc3eb8,0xbf5f3f6f,0x3f77becf,0xbe893f6a,
0x3f42bf7c,0x3f273e2f,0x3d97bf51,0x3f7fbf13,0xbf4a3cc9,0x3f1dbf80,0xbf7e3f39,0xbdfbbf31,0xbf7b3f55,0xbe48bf0e,0xbf7b3f55,0xbe48bf0e,
0x3e483f0e,0xbf7b3f55,0x3e483f0e,0xbf7b3f55,0x3f7bbf55,0x3e483f0e,0x3f7bbf55,0x3e483f0e,0xbe48bf0e,0x3f7bbf55,0xbe48bf0e,0x3f7bbf55,
0xbf7f3f51,0xbd97bf13,0xbf423e2f,0x3f27bf7c,0xbdfb3f39,0xbf7e3f31,0xbf4a3f80,0xbf1dbcc9,0x3f73bf09,0xbea13f58,0x3ee63e60,0xbf653f7a,
0x3efcbf6f,0x3f5fbeb8,0x3f77bf6a,0x3e893ecf,0xbf803f4e,0x3d49bf18,0x3d49bf18,0x3f80bf4e,0xbedb3f5c,0xbf673f04,0xbf673f04,0x3edbbf5c,
0x3f2cbe16,0xbf3e3f7d,0xbf3e3f7d,0xbf2c3e16,0x3f71bf78,0x3eac3e79,0x3eac3e79,0xbf713f78,0xbf7c3f4a,0x3e2fbf1d,0x3f51bf7e,0x3f13bdfb,
0xbf313f73,0xbf393ea1,0xbcc9bee6,0x3f80bf65,0x3e603e89,0xbf7a3f77,0xbf583efc,0x3f09bf5f,0x3f6fbf27,0xbeb83f42,0xbf6a3f7f,0xbecfbd97,
0xbf753f46,0x3e95bf22,0x3f75bf46,0xbe953f22,0xbf623f7f,0xbef13dc9,0x3f62bf7f,0x3ef1bdc9,0xbe953f22,0xbf753f46,0x3e95bf22,0x3f75bf46,
0x3ef1bdc9,0xbf623f7f,0xbef13dc9,0x3f62bf7f,0xbf6a3f42,0x3ecfbf27,0x3eb8bd97,0xbf6f3f7f,0xbf7c3f7e,0xbe2fbdfb,0x3f51bf1d,0xbf133f4a,
0xbf393f65,0xbf313ee6,0x3f80bf73,0xbcc93ea1,0xbe603efc,0xbf7a3f5f,0x3f58bf77,0x3f09be89,0xbf5c3f3e,0x3f04bf2c,0xbf043f2c,0xbf5c3f3e,
0xbf7d3f71,0x3e16beac,0xbe163eac,0xbf7d3f71,0xbf783f80,0xbe793d49,0x3e79bd49,0xbf783f80,0xbf4e3f67,0xbf183edb,0x3f18bedb,0xbf4e3f67,
0xbf4a3f39,0x3f1dbf31,0xbf7e3f80,0xbdfb3cc9,0xbf653f58,0x3ee6bf09,0xbf733f7a,0xbea13e60,0xbf773f6f,0x3e89beb8,0xbf5f3f6a,0xbefc3ecf,
0xbf7f3f7c,0x3d97be2f,0xbf423f51,0xbf273f13,0x3f803f80,0xbf353f35,0x3f803f80,0xbf353f35,0x3f803f80,0xbf353f35,0x3f803f80,0xbf353f35,
0x3f803f80,0xbf353f35,0x3f803f80,0xbf353f35,0x3f803f80,0xbf353f35,0x3f803f80,0xbf353f35,0xbdfbbcc9,0xbf7ebf80,0xbf4abf39,0xbf1dbf31,
0xbea1be60,0xbf73bf7a,0xbf65bf58,0xbee6bf09,0xbefcbecf,0xbf5fbf6a,0xbf77bf6f,0xbe89beb8,0xbf27bf13,0xbf42bf51,0xbf7fbf7c,0xbd97be2f,
0xbf78bf80,0x3e793d49,0x3e793d49,0x3f783f80,0xbf4ebf67,0x3f183edb,0x3f183edb,0x3f4e3f67,0xbf04bf2c,0x3f5c3f3e,0x3f5c3f3e,0x3f043f2c,
0xbe16beac,0x3f7d3f71,0x3f7d3f71,0x3e163eac,0x3eb83d97,0x3f6f3f7f,0x3ecf3f27,0xbf6abf42,0x3f513f1d,0x3f133f4a,0xbe2f3dfb,0xbf7cbf7e,
0x3f803f73,0x3cc93ea1,0xbf31bee6,0xbf39bf65,0x3f583f77,0xbf09be89,0xbf7abf5f,0xbe60befc,0x3f623f7f,0xbef1bdc9,0xbf62bf7f,0x3ef13dc9,
0x3e953f22,0xbf75bf46,0xbe95bf22,0x3f753f46,0xbef1bdc9,0xbf62bf7f,0x3ef13dc9,0x3f623f7f,0xbf75bf46,0xbe95bf22,0x3f753f46,0x3e953f22,
0xbf13bdfb,0xbf51bf7e,0x3f7c3f4a,0x3e2f3f1d,0xbf80bf65,0x3cc9bee6,0x3f313f73,0xbf39bea1,0xbf09bf5f,0x3f583efc,0xbe603e89,0xbf7abf77,
0x3ecfbd97,0x3f6a3f7f,0xbf6fbf27,0xbeb8bf42,0xbf3ebf7d,0x3f2c3e16,0xbf2cbe16,0xbf3ebf7d,0x3eacbe79,0x3f713f78,0xbf71bf78,0x3eacbe79,
0x3f803f4e,0x3d493f18,0xbd49bf18,0x3f803f4e,0x3edb3f5c,0xbf67bf04,0x3f673f04,0x3edb3f5c,0x3f423e2f,0x3f273f7c,0x3d97bf13,0x3f7f3f51,
0x3f4a3f80,0xbf1d3cc9,0x3f7e3f31,0x3dfb3f39,0xbee63e60,0xbf65bf7a,0x3ea13f58,0xbf73bf09,0xbf77bf6a,0x3e89becf,0xbf5fbeb8,0xbefcbf6f,
0x3f0e3f7b,0xbf55be48,0x3f0e3f7b,0xbf55be48,0xbf55be48,0xbf0ebf7b,0xbf55be48,0xbf0ebf7b,0xbf0ebf7b,0x3f553e48,0xbf0ebf7b,0x3f553e48,
0x3f553e48,0x3f0e3f7b,0x3f553e48,0x3f0e3f7b,0xbf65be60,0xbee6bf7a,0xbf73bf58,0x3ea1bf09,0xbe89bf6a,0x3f773ecf,0x3efcbeb8,0x3f5f3f6f,
0x3f7f3f13,0x3d973f51,0x3f423f7c,0xbf273e2f,0xbdfb3f31,0xbf7ebf39,0xbf4abcc9,0xbf1dbf80,0xbeacbf78,0x3f713e79,0x3f713e79,0x3eac3f78,
0x3f803f18,0xbd493f4e,0xbd493f4e,0xbf80bf18,0xbedb3f04,0xbf67bf5c,0xbf67bf5c,0x3edbbf04,0xbf2cbf7d,0x3f3ebe16,0x3f3ebe16,0x3f2c3f7d,
0x3f7a3e89,0x3e603f77,0xbf093efc,0xbf58bf5f,0xbeb83f27,0xbf6fbf42,0xbecfbf7f,0x3f6a3d97,0xbf13bf7e,0x3f51bdfb,0x3f7c3f1d,0xbe2f3f4a,
0x3f803ee6,0x3cc93f65,0xbf313ea1,0xbf39bf73,0x3dc93f75,0xbf7fbe95,0xbdc9bf75,0x3f7f3e95,0xbf46bf62,0x3f22bef1,0x3f463f62,0xbf223ef1,
0x3f7f3e95,0x3dc93f75,0xbf7fbe95,0xbdc9bf75,0xbf223ef1,0xbf46bf62,0x3f22bef1,0x3f463f62,0xbf80bea1,0x3cc9bf73,0x3f313f65,0xbf393ee6,
0x3f58be89,0x3f093f77,0xbf7abefc,0x3e60bf5f,0xbecf3f42,0xbf6abf27,0x3f6fbd97,0x3eb83f7f,0xbe2fbf7e,0x3f7c3dfb,0xbf133f1d,0xbf51bf4a,
0x3e16bf71,0x3f7d3eac,0xbf7dbeac,0x3e16bf71,0x3e793f80,0xbf783d49,0x3f78bd49,0x3e793f80,0xbf18bf67,0x3f4ebedb,0xbf4e3edb,0xbf18bf67,
0x3f5c3f2c,0xbf043f3e,0x3f04bf3e,0x3f5c3f2c,0x3f773eb8,0xbe893f6f,0x3f5fbecf,0x3efc3f6a,0xbf7fbe2f,0x3d97bf7c,0xbf423f13,0xbf27bf51,
0x3f7ebcc9,0x3dfb3f80,0x3f1dbf39,0x3f4a3f31,0xbf733e60,0xbea1bf7a,0xbee63f58,0xbf65bf09,0xbec43f6d,0xbf6dbec4,0xbec43f6d,0xbf6dbec4,
0x3ec4bf6d,0x3f6d3ec4,0x3ec4bf6d,0x3f6d3ec4,0xbec43f6d,0xbf6dbec4,0xbec43f6d,0xbf6dbec4,0x3ec4bf6d,0x3f6d3ec4,0x3ec4bf6d,0x3f6d3ec4,
0xbf5fbecf,0x3efcbf6a,0xbe89bf6f,0x3f77beb8,0x3f423f13,0xbf273f51,0x3d973f7c,0xbf7f3e2f,0xbf1dbf39,0x3f4abf31,0x3dfbbf80,0x3f7e3cc9,
0x3ee63f58,0xbf653f09,0xbea13f7a,0xbf73be60,0x3f18bf67,0x3f4e3edb,0x3f4e3edb,0xbf183f67,0xbf5c3f2c,0xbf04bf3e,0xbf04bf3e,0x3f5cbf2c,
0x3f7dbeac,0x3e163f71,0x3e163f71,0xbf7d3eac,0xbf78bd49,0x3e79bf80,0x3e79bf80,0x3f783d49,0x3f393ee6,0xbf313f65,0xbf803ea1,0xbcc9bf73,
0xbe60bf5f,0x3f7abefc,0x3f583e89,0xbf093f77,0xbeb83f7f,0xbf6fbd97,0xbecfbf42,0x3f6abf27,0x3f51bf4a,0x3f133f1d,0xbe2f3f7e,0xbf7c3dfb,
0xbf463f62,0xbf22bef1,0x3f46bf62,0x3f223ef1,0x3f7fbe95,0xbdc93f75,0xbf7f3e95,0x3dc9bf75,0xbf22bef1,0x3f46bf62,0x3f223ef1,0xbf463f62,
0xbdc93f75,0xbf7f3e95,0x3dc9bf75,0x3f7fbe95,0xbf09befc,0x3f58bf5f,0xbe603f77,0xbf7a3e89,0xbecf3f7f,0xbf6a3d97,0x3f6fbf42,0x3eb83f27,
0x3f7cbf1d,0x3e2f3f4a,0xbf51bdfb,0x3f13bf7e,0xbf31bea1,0x3f39bf73,0xbcc93f65,0xbf803ee6,0x3f67bf5c,0x3edb3f04,0xbedbbf04,0x3f67bf5c,
0xbf3ebe16,0x3f2cbf7d,0xbf2c3f7d,0xbf3ebe16,0xbeac3f78,0xbf713e79,0x3f71be79,0xbeac3f78,0x3f80bf18,0x3d493f4e,0xbd49bf4e,0x3f80bf18,
0x3ea13f09,0xbf733f58,0x3f65be60,0xbee63f7a,0x3f5fbf6f,0x3efc3eb8,0x3e89bf6a,0x3f77becf,0xbf27be2f,0x3f42bf7c,0xbf7f3f13,0x3d97bf51,
0xbf1d3f80,0xbf4a3cc9,0x3dfb3f31,0xbf7e3f39,0xbf7b3f55,0xbe48bf0e,0xbf7b3f55,0xbe48bf0e,0x3e483f0e,0xbf7b3f55,0x3e483f0e,0xbf7b3f55,
0x3f7bbf55,0x3e483f0e,0x3f7bbf55,0x3e483f0e,0xbe48bf0e,0x3f7bbf55,0xbe48bf0e,0x3f7bbf55,0xbd97bf13,0x3f7fbf51,0x3f27bf7c,0x3f42be2f,
0xbf7e3f31,0x3dfbbf39,0xbf1dbcc9,0x3f4abf80,0xbea13f58,0xbf733f09,0xbf653f7a,0xbee6be60,0x3f5fbeb8,0xbefc3f6f,0x3e893ecf,0xbf773f6a,
0x3f80bf4e,0xbd493f18,0xbd493f18,0xbf803f4e,0x3edbbf5c,0x3f67bf04,0x3f67bf04,0xbedb3f5c,0xbf2c3e16,0x3f3ebf7d,0x3f3ebf7d,0x3f2cbe16,
0xbf713f78,0xbeacbe79,0xbeacbe79,0x3f71bf78,0xbe2f3f1d,0xbf7c3f4a,0xbf133dfb,0x3f51bf7e,0x3f39bea1,0xbf313f73,0xbf803f65,0xbcc9bee6,
0x3f7abf77,0x3e603e89,0xbf093f5f,0xbf583efc,0x3eb8bf42,0x3f6fbf27,0x3ecf3d97,0xbf6a3f7f,0xbf753f46,0x3e95bf22,0x3f75bf46,0xbe953f22,
0xbf623f7f,0xbef13dc9,0x3f62bf7f,0x3ef1bdc9,0xbe953f22,0xbf753f46,0x3e95bf22,0x3f75bf46,0x3ef1bdc9,0xbf623f7f,0xbef13dc9,0x3f62bf7f,
0x3ecfbf27,0x3f6abf42,0xbf6f3f7f,0xbeb83d97,0xbe2fbdfb,0x3f7cbf7e,0xbf133f4a,0xbf513f1d,0xbf313ee6,0x3f39bf65,0xbcc93ea1,0xbf803f73,
0xbf7a3f5f,0x3e60befc,0x3f09be89,0xbf583f77,0x3f5cbf3e,0xbf043f2c,0x3f04bf2c,0x3f5cbf3e,0x3f7dbf71,0xbe163eac,0x3e16beac,0x3f7dbf71,
0x3f78bf80,0x3e79bd49,0xbe793d49,0x3f78bf80,0x3f4ebf67,0x3f18bedb,0xbf183edb,0x3f4ebf67,0xbf1d3f31,0xbf4a3f39,0x3dfbbcc9,0xbf7e3f80,
0xbee63f09,0xbf653f58,0x3ea1be60,0xbf733f7a,0xbe893eb8,0xbf773f6f,0x3efcbecf,0xbf5f3f6a,0xbd973e2f,0xbf7f3f7c,0x3f27bf13,0xbf423f51,
0x3f803f80,0xbf353f35,0x3f803f80,0xbf353f35,0x3f803f80,0xbf353f35,0x3f803f80,0xbf353f35,0x3f803f80,0xbf353f35,0x3f803f80,0xbf353f35,
0x3f803f80,0xbf353f35,0x3f803f80,0xbf353f35,0xbf7ebf80,0x3dfb3cc9,0xbf1dbf31,0x3f4a3f39,0xbf73bf7a,0x3ea13e60,0xbee6bf09,0x3f653f58,
0xbf5fbf6a,0x3efc3ecf,0xbe89beb8,0x3f773f6f,0xbf42bf51,0x3f273f13,0xbd97be2f,0x3f7f3f7c,0x3f783f80,0xbe79bd49,0xbe79bd49,0xbf78bf80,
0x3f4e3f67,0xbf18bedb,0xbf18bedb,0xbf4ebf67,0x3f043f2c,0xbf5cbf3e,0xbf5cbf3e,0xbf04bf2c,0x3e163eac,0xbf7dbf71,0xbf7dbf71,0xbe16beac,
0xbf6fbf7f,0x3eb83d97,0x3f6a3f42,0x3ecf3f27,0xbf13bf4a,0x3f513f1d,0x3f7c3f7e,0xbe2f3dfb,0xbcc9bea1,0x3f803f73,0x3f393f65,0xbf31bee6,
0x3f093e89,0x3f583f77,0x3e603efc,0xbf7abf5f,0x3f623f7f,0xbef1bdc9,0xbf62bf7f,0x3ef13dc9,0x3e953f22,0xbf75bf46,0xbe95bf22,0x3f753f46,
0xbef1bdc9,0xbf62bf7f,0x3ef13dc9,0x3f623f7f,0xbf75bf46,0xbe95bf22,0x3f753f46,0x3e953f22,0xbf51bf7e,0x3f133dfb,0x3e2f3f1d,0xbf7cbf4a,
0x3cc9bee6,0x3f803f65,0xbf39bea1,0xbf31bf73,0x3f583efc,0x3f093f5f,0xbf7abf77,0x3e60be89,0x3f6a3f7f,0xbecf3d97,0xbeb8bf42,0x3f6f3f27,
0x3f3e3f7d,0xbf2cbe16,0x3f2c3e16,0x3f3e3f7d,0xbeac3e79,0xbf71bf78,0x3f713f78,0xbeac3e79,0xbf80bf4e,0xbd49bf18,0x3d493f18,0xbf80bf4e,
0xbedbbf5c,0x3f673f04,0xbf67bf04,0xbedbbf5c,0xbf27bf7c,0x3f423e2f,0xbf7fbf51,0x3d97bf13,0x3f1dbcc9,0x3f4a3f80,0xbdfbbf39,0x3f7e3f31,
0x3f653f7a,0xbee63e60,0x3f733f09,0x3ea13f58,0xbe893ecf,0xbf77bf6a,0x3efc3f6f,0xbf5fbeb8,0x3f0e3f7b,0xbf55be48,0x3f0e3f7b,0xbf55be48,
0xbf55be48,0xbf0ebf7b,0xbf55be48,0xbf0ebf7b,0xbf0ebf7b,0x3f553e48,0xbf0ebf7b,0x3f553e48,0x3f553e48,0x3f0e3f7b,0x3f553e48,0x3f0e3f7b,
0xbee6bf7a,0x3f653e60,0x3ea1bf09,0x3f733f58,0x3f773ecf,0x3e893f6a,0x3f5f3f6f,0xbefc3eb8,0x3d973f51,0xbf7fbf13,0xbf273e2f,0xbf42bf7c,
0xbf7ebf39,0x3dfbbf31,0xbf1dbf80,0x3f4a3cc9,0x3eac3f78,0xbf71be79,0xbf71be79,0xbeacbf78,0xbf80bf18,0x3d49bf4e,0x3d49bf4e,0x3f803f18,
0x3edbbf04,0x3f673f5c,0x3f673f5c,0xbedb3f04,0x3f2c3f7d,0xbf3e3e16,0xbf3e3e16,0xbf2cbf7d,0xbe60bf77,0x3f7a3e89,0x3f583f5f,0xbf093efc,
0x3f6f3f42,0xbeb83f27,0xbf6abd97,0xbecfbf7f,0xbf513dfb,0xbf13bf7e,0x3e2fbf4a,0x3f7c3f1d,0xbcc9bf65,0x3f803ee6,0x3f393f73,0xbf313ea1,
0x3dc93f75,0xbf7fbe95,0xbdc9bf75,0x3f7f3e95,0xbf46bf62,0x3f22bef1,0x3f463f62,0xbf223ef1,0x3f7f3e95,0x3dc93f75,0xbf7fbe95,0xbdc9bf75,
0xbf223ef1,0xbf46bf62,0x3f22bef1,0x3f463f62,0x3cc9bf73,0x3f803ea1,0xbf393ee6,0xbf31bf65,0x3f093f77,0xbf583e89,0x3e60bf5f,0x3f7a3efc,
0xbf6abf27,0x3ecfbf42,0x3eb83f7f,0xbf6f3d97,0x3f7c3dfb,0x3e2f3f7e,0xbf51bf4a,0x3f13bf1d,0xbe163f71,0xbf7dbeac,0x3f7d3eac,0xbe163f71,
0xbe79bf80,0x3f78bd49,0xbf783d49,0xbe79bf80,0x3f183f67,0xbf4e3edb,0x3f4ebedb,0x3f183f67,0xbf5cbf2c,0x3f04bf3e,0xbf043f3e,0xbf5cbf2c,
0x3e89bf6f,0x3f773eb8,0xbefcbf6a,0x3f5fbecf,0xbd973f7c,0xbf7fbe2f,0x3f273f51,0xbf423f13,0xbdfbbf80,0x3f7ebcc9,0xbf4abf31,0x3f1dbf39,
0x3ea13f7a,0xbf733e60,0x3f653f09,0xbee63f58,0xbec43f6d,0xbf6dbec4,0xbec43f6d,0xbf6dbec4,0x3ec4bf6d,0x3f6d3ec4,0x3ec4bf6d,0x3f6d3ec4,
0xbec43f6d,0xbf6dbec4,0xbec43f6d,0xbf6dbec4,0x3ec4bf6d,0x3f6d3ec4,0x3ec4bf6d,0x3f6d3ec4,0x3efcbf6a,0x3f5f3ecf,0x3f77beb8,0x3e893f6f,
0xbf273f51,0xbf42bf13,0xbf7f3e2f,0xbd97bf7c,0x3f4abf31,0x3f1d3f39,0x3f7e3cc9,0xbdfb3f80,0xbf653f09,0xbee6bf58,0xbf73be60,0x3ea1bf7a,
0xbf183f67,0xbf4ebedb,0xbf4ebedb,0x3f18bf67,0x3f5cbf2c,0x3f043f3e,0x3f043f3e,0xbf5c3f2c,0xbf7d3eac,0xbe16bf71,0xbe16bf71,0x3f7dbeac,
0x3f783d49,0xbe793f80,0xbe793f80,0xbf78bd49,0x3f31bf65,0x3f393ee6,0x3cc93f73,0xbf803ea1,0xbf7a3efc,0xbe60bf5f,0x3f09bf77,0x3f583e89,
0x3f6f3d97,0xbeb83f7f,0xbf6a3f27,0xbecfbf42,0xbf13bf1d,0x3f51bf4a,0x3f7cbdfb,0xbe2f3f7e,0xbf463f62,0xbf22bef1,0x3f46bf62,0x3f223ef1,
0x3f7fbe95,0xbdc93f75,0xbf7f3e95,0x3dc9bf75,0xbf22bef1,0x3f46bf62,0x3f223ef1,0xbf463f62,0xbdc93f75,0xbf7f3e95,0x3dc9bf75,0x3f7fbe95,
0x3f58bf5f,0x3f093efc,0xbf7a3e89,0x3e60bf77,0xbf6a3d97,0x3ecfbf7f,0x3eb83f27,0xbf6f3f42,0x3e2f3f4a,0xbf7c3f1d,0x3f13bf7e,0x3f513dfb,
0x3f39bf73,0x3f313ea1,0xbf803ee6,0x3cc9bf65,0xbf673f5c,0xbedbbf04,0x3edb3f04,0xbf673f5c,0x3f3e3e16,0xbf2c3f7d,0x3f2cbf7d,0x3f3e3e16,
0x3eacbf78,0x3f71be79,0xbf713e79,0x3eacbf78,0xbf803f18,0xbd49bf4e,0x3d493f4e,0xbf803f18,0x3f73bf58,0x3ea13f09,0x3ee6bf7a,0x3f65be60,
0xbefcbeb8,0x3f5fbf6f,0xbf773ecf,0x3e89bf6a,0xbf423f7c,0xbf27be2f,0xbd973f51,0xbf7f3f13,0x3f4abcc9,0xbf1d3f80,0x3f7ebf39,0x3dfb3f31,
0xbf7b3f55,0xbe48bf0e,0xbf7b3f55,0xbe48bf0e,0x3e483f0e,0xbf7b3f55,0x3e483f0e,0xbf7b3f55,0x3f7bbf55,0x3e483f0e,0x3f7bbf55,0x3e483f0e,
0xbe48bf0e,0x3f7bbf55,0xbe48bf0e,0x3f7bbf55,0x3f7fbf51,0x3d973f13,0x3f42be2f,0xbf273f7c,0x3dfbbf39,0x3f7ebf31,0x3f4abf80,0x3f1d3cc9,
0xbf733f09,0x3ea1bf58,0xbee6be60,0x3f65bf7a,0xbefc3f6f,0xbf5f3eb8,0xbf773f6a,0xbe89becf,0xbf803f4e,0x3d49bf18,0x3d49bf18,0x3f80bf4e,
0xbedb3f5c,0xbf673f04,0xbf673f04,0x3edbbf5c,0x3f2cbe16,0xbf3e3f7d,0xbf3e3f7d,0xbf2c3e16,0x3f71bf78,0x3eac3e79,0x3eac3e79,0xbf713f78,
0x3f7cbf4a,0xbe2f3f1d,0xbf513f7e,0xbf133dfb,0x3f31bf73,0x3f39bea1,0x3cc93ee6,0xbf803f65,0xbe60be89,0x3f7abf77,0x3f58befc,0xbf093f5f,
0xbf6f3f27,0x3eb8bf42,0x3f6abf7f,0x3ecf3d97,0xbf753f46,0x3e95bf22,0x3f75bf46,0xbe953f22,0xbf623f7f,0xbef13dc9,0x3f62bf7f,0x3ef1bdc9,
0xbe953f22,0xbf753f46,0x3e95bf22,0x3f75bf46,0x3ef1bdc9,0xbf623f7f,0xbef13dc9,0x3f62bf7f,0x3f6abf42,0xbecf3f27,0xbeb83d97,0x3f6fbf7f,
0x3f7cbf7e,0x3e2f3dfb,0xbf513f1d,0x3f13bf4a,0x3f39bf65,0x3f31bee6,0xbf803f73,0x3cc9bea1,0x3e60befc,0x3f7abf5f,0xbf583f77,0xbf093e89,
0xbf5c3f3e,0x3f04bf2c,0xbf043f2c,0xbf5c3f3e,0xbf7d3f71,0x3e16beac,0xbe163eac,0xbf7d3f71,0xbf783f80,0xbe793d49,0x3e79bd49,0xbf783f80,
0xbf4e3f67,0xbf183edb,0x3f18bedb,0xbf4e3f67,0x3f4abf39,0xbf1d3f31,0x3f7ebf80,0x3dfbbcc9,0x3f65bf58,0xbee63f09,0x3f73bf7a,0x3ea1be60,
0x3f77bf6f,0xbe893eb8,0x3f5fbf6a,0x3efcbecf,0x3f7fbf7c,0xbd973e2f,0x3f42bf51,0x3f27bf13,0x3f803f80,0xbf353f35,0x3f803f80,0xbf353f35,
0x3f803f80,0xbf353f35,0x3f803f80,0xbf353f35,0x3f803f80,0xbf353f35,0x3f803f80,0xbf353f35,0x3f803f80,0xbf353f35,0x3f803f80,0xbf353f35,
0x3dfb3cc9,0x3f7e3f80,0x3f4a3f39,0x3f1d3f31,0x3ea13e60,0x3f733f7a,0x3f653f58,0x3ee63f09,0x3efc3ecf,0x3f5f3f6a,0x3f773f6f,0x3e893eb8,
0x3f273f13,0x3f423f51,0x3f7f3f7c,0x3d973e2f,0xbf78bf80,0x3e793d49,0x3e793d49,0x3f783f80,0xbf4ebf67,0x3f183edb,0x3f183edb,0x3f4e3f67,
0xbf04bf2c,0x3f5c3f3e,0x3f5c3f3e,0x3f043f2c,0xbe16beac,0x3f7d3f71,0x3f7d3f71,0x3e163eac,0xbeb8bd97,0xbf6fbf7f,0xbecfbf27,0x3f6a3f42,
0xbf51bf1d,0xbf13bf4a,0x3e2fbdfb,0x3f7c3f7e,0xbf80bf73,0xbcc9bea1,0x3f313ee6,0x3f393f65,0xbf58bf77,0x3f093e89,0x3f7a3f5f,0x3e603efc,
0x3f623f7f,0xbef1bdc9,0xbf62bf7f,0x3ef13dc9,0x3e953f22,0xbf75bf46,0xbe95bf22,0x3f753f46,0xbef1bdc9,0xbf62bf7f,0x3ef13dc9,0x3f623f7f,
0xbf75bf46,0xbe95bf22,0x3f753f46,0x3e953f22,0x3f133dfb,0x3f513f7e,0xbf7cbf4a,0xbe2fbf1d,0x3f803f65,0xbcc93ee6,0xbf31bf73,0x3f393ea1,
0x3f093f5f,0xbf58befc,0x3e60be89,0x3f7a3f77,0xbecf3d97,0xbf6abf7f,0x3f6f3f27,0x3eb83f42,0xbf3ebf7d,0x3f2c3e16,0xbf2cbe16,0xbf3ebf7d,
0x3eacbe79,0x3f713f78,0xbf71bf78,0x3eacbe79,0x3f803f4e,0x3d493f18,0xbd49bf18,0x3f803f4e,0x3edb3f5c,0xbf67bf04,0x3f673f04,0x3edb3f5c,
0xbf42be2f,0xbf27bf7c,0xbd973f13,0xbf7fbf51,0xbf4abf80,0x3f1dbcc9,0xbf7ebf31,0xbdfbbf39,0x3ee6be60,0x3f653f7a,0xbea1bf58,0x3f733f09,
0x3f773f6a,0xbe893ecf,0x3f5f3eb8,0x3efc3f6f,0x3f0e3f7b,0xbf55be48,0x3f0e3f7b,0xbf55be48,0xbf55be48,0xbf0ebf7b,0xbf55be48,0xbf0ebf7b,
0xbf0ebf7b,0x3f553e48,0xbf0ebf7b,0x3f553e48,0x3f553e48,0x3f0e3f7b,0x3f553e48,0x3f0e3f7b,0x3f653e60,0x3ee63f7a,0x3f733f58,0xbea13f09,
0x3e893f6a,0xbf77becf,0xbefc3eb8,0xbf5fbf6f,0xbf7fbf13,0xbd97bf51,0xbf42bf7c,0x3f27be2f,0x3dfbbf31,0x3f7e3f39,0x3f4a3cc9,0x3f1d3f80,
0xbeacbf78,0x3f713e79,0x3f713e79,0x3eac3f78,0x3f803f18,0xbd493f4e,0xbd493f4e,0xbf80bf18,0xbedb3f04,0xbf67bf5c,0xbf67bf5c,0x3edbbf04,
0xbf2cbf7d,0x3f3ebe16,0x3f3ebe16,0x3f2c3f7d,0xbf7abe89,0xbe60bf77,0x3f09befc,0x3f583f5f,0x3eb8bf27,0x3f6f3f42,0x3ecf3f7f,0xbf6abd97,
0x3f133f7e,0xbf513dfb,0xbf7cbf1d,0x3e2fbf4a,0xbf80bee6,0xbcc9bf65,0x3f31bea1,0x3f393f73,0x3dc93f75,0xbf7fbe95,0xbdc9bf75,0x3f7f3e95,
0xbf46bf62,0x3f22bef1,0x3f463f62,0xbf223ef1,0x3f7f3e95,0x3dc93f75,0xbf7fbe95,0xbdc9bf75,0xbf223ef1,0xbf46bf62,0x3f22bef1,0x3f463f62,
0x3f803ea1,0xbcc93f73,0xbf31bf65,0x3f39bee6,0xbf583e89,0xbf09bf77,0x3f7a3efc,0xbe603f5f,0x3ecfbf42,0x3f6a3f27,0xbf6f3d97,0xbeb8bf7f,
0x3e2f3f7e,0xbf7cbdfb,0x3f13bf1d,0x3f513f4a,0x3e16bf71,0x3f7d3eac,0xbf7dbeac,0x3e16bf71,0x3e793f80,0xbf783d49,0x3f78bd49,0x3e793f80,
0xbf18bf67,0x3f4ebedb,0xbf4e3edb,0xbf18bf67,0x3f5c3f2c,0xbf043f3e,0x3f04bf3e,0x3f5c3f2c,0xbf77beb8,0x3e89bf6f,0xbf5f3ecf,0xbefcbf6a,
0x3f7f3e2f,0xbd973f7c,0x3f42bf13,0x3f273f51,0xbf7e3cc9,0xbdfbbf80,0xbf1d3f39,0xbf4abf31,0x3f73be60,0x3ea13f7a,0x3ee6bf58,0x3f653f09,
0xbec43f6d,0xbf6dbec4,0xbec43f6d,0xbf6dbec4,0x3ec4bf6d,0x3f6d3ec4,0x3ec4bf6d,0x3f6d3ec4,0xbec43f6d,0xbf6dbec4,0xbec43f6d,0xbf6dbec4,
0x3ec4bf6d,0x3f6d3ec4,0x3ec4bf6d,0x3f6d3ec4,0x3f5f3ecf,0xbefc3f6a,0x3e893f6f,0xbf773eb8,0xbf42bf13,0x3f27bf51,0xbd97bf7c,0x3f7fbe2f,
0x3f1d3f39,0xbf4a3f31,0xbdfb3f80,0xbf7ebcc9,0xbee6bf58,0x3f65bf09,0x3ea1bf7a,0x3f733e60,0x3f18bf67,0x3f4e3edb,0x3f4e3edb,0xbf183f67,
0xbf5c3f2c,0xbf04bf3e,0xbf04bf3e,0x3f5cbf2c,0x3f7dbeac,0x3e163f71,0x3e163f71,0xbf7d3eac,0xbf78bd49,0x3e79bf80,0x3e79bf80,0x3f783d49,
0xbf39bee6,0x3f31bf65,0x3f80bea1,0x3cc93f73,0x3e603f5f,0xbf7a3efc,0xbf58be89,0x3f09bf77,0x3eb8bf7f,0x3f6f3d97,0x3ecf3f42,0xbf6a3f27,
0xbf513f4a,0xbf13bf1d,0x3e2fbf7e,0x3f7cbdfb,0xbf463f62,0xbf22bef1,0x3f46bf62,0x3f223ef1,0x3f7fbe95,0xbdc93f75,0xbf7f3e95,0x3dc9bf75,
0xbf22bef1,0x3f46bf62,0x3f223ef1,0xbf463f62,0xbdc93f75,0xbf7f3e95,0x3dc9bf75,0x3f7fbe95,0x3f093efc,0xbf583f5f,0x3e60bf77,0x3f7abe89,
0x3ecfbf7f,0x3f6abd97,0xbf6f3f42,0xbeb8bf27,0xbf7c3f1d,0xbe2fbf4a,0x3f513dfb,0xbf133f7e,0x3f313ea1,0xbf393f73,0x3cc9bf65,0x3f80bee6,
0x3f67bf5c,0x3edb3f04,0xbedbbf04,0x3f67bf5c,0xbf3ebe16,0x3f2cbf7d,0xbf2c3f7d,0xbf3ebe16,0xbeac3f78,0xbf713e79,0x3f71be79,0xbeac3f78,
0x3f80bf18,0x3d493f4e,0xbd49bf4e,0x3f80bf18,0xbea1bf09,0x3f73bf58,0xbf653e60,0x3ee6bf7a,0xbf5f3f6f,0xbefcbeb8,0xbe893f6a,0xbf773ecf,
0x3f273e2f,0xbf423f7c,0x3f7fbf13,0xbd973f51,0x3f1dbf80,0x3f4abcc9,0xbdfbbf31,0x3f7ebf39,0xbf7b3f55,0xbe48bf0e,0xbf7b3f55,0xbe48bf0e,
0x3e483f0e,0xbf7b3f55,0x3e483f0e,0xbf7b3f55,0x3f7bbf55,0x3e483f0e,0x3f7bbf55,0x3e483f0e,0xbe48bf0e,0x3f7bbf55,0xbe48bf0e,0x3f7bbf55,
0x3d973f13,0xbf7f3f51,0xbf273f7c,0xbf423e2f,0x3f7ebf31,0xbdfb3f39,0x3f1d3cc9,0xbf4a3f80,0x3ea1bf58,0x3f73bf09,0x3f65bf7a,0x3ee63e60,
0xbf5f3eb8,0x3efcbf6f,0xbe89becf,0x3f77bf6a,0x3f80bf4e,0xbd493f18,0xbd493f18,0xbf803f4e,0x3edbbf5c,0x3f67bf04,0x3f67bf04,0xbedb3f5c,
0xbf2c3e16,0x3f3ebf7d,0x3f3ebf7d,0x3f2cbe16,0xbf713f78,0xbeacbe79,0xbeacbe79,0x3f71bf78,0x3e2fbf1d,0x3f7cbf4a,0x3f13bdfb,0xbf513f7e,
0xbf393ea1,0x3f31bf73,0x3f80bf65,0x3cc93ee6,0xbf7a3f77,0xbe60be89,0x3f09bf5f,0x3f58befc,0xbeb83f42,0xbf6f3f27,0xbecfbd97,0x3f6abf7f,
0xbf753f46,0x3e95bf22,0x3f75bf46,0xbe953f22,0xbf623f7f,0xbef13dc9,0x3f62bf7f,0x3ef1bdc9,0xbe953f22,0xbf753f46,0x3e95bf22,0x3f75bf46,
0x3ef1bdc9,0xbf623f7f,0xbef13dc9,0x3f62bf7f,0xbecf3f27,0xbf6a3f42,0x3f6fbf7f,0x3eb8bd97,0x3e2f3dfb,0xbf7c3f7e,0x3f13bf4a,0x3f51bf1d,
0x3f31bee6,0xbf393f65,0x3cc9bea1,0x3f80bf73,0x3f7abf5f,0xbe603efc,0xbf093e89,0x3f58bf77,0x3f5cbf3e,0xbf043f2c,0x3f04bf2c,0x3f5cbf3e,
0x3f7dbf71,0xbe163eac,0x3e16beac,0x3f7dbf71,0x3f78bf80,0x3e79bd49,0xbe793d49,0x3f78bf80,0x3f4ebf67,0x3f18bedb,0xbf183edb,0x3f4ebf67,
0x3f1dbf31,0x3f4abf39,0xbdfb3cc9,0x3f7ebf80,0x3ee6bf09,0x3f65bf58,0xbea13e60,0x3f73bf7a,0x3e89beb8,0x3f77bf6f,0xbefc3ecf,0x3f5fbf6a,
0x3d97be2f,0x3f7fbf7c,0xbf273f13,0x3f42bf51,0x3f803f80,0xbf803f80,0x3f803f80,0xbf803f80,0x3f803f80,0xbf803f80,0x3f803f80,0xbf803f80,
0x3f803f80,0xbf803f80,0x3f803f80,0xbf803f80,0x3f803f80,0xbf803f80,0x3f803f80,0xbf803f80,0x3f7d3f80,0xbe16bd49,0x3f183f2c,0xbf4ebf3e,
0x3f713f78,0xbeacbe79,0x3edb3f04,0xbf67bf5c,0x3f5c3f67,0xbf04bedb,0x3e793eac,0xbf78bf71,0x3f3e3f4e,0xbf2cbf18,0x3d493e16,0xbf80bf7d,
0x3f753f7f,0xbe95bdc9,0xbe95bdc9,0xbf75bf7f,0x3f463f62,0xbf22bef1,0xbf22bef1,0xbf46bf62,0x3ef13f22,0xbf62bf46,0xbf62bf46,0xbef1bf22,
0x3dc93e95,0xbf7fbf75,0xbf7fbf75,0xbdc9be95,0x3f673f7d,0xbedbbe16,0xbf71bf4e,0xbeacbf18,0x3f043f3e,0xbf5cbf2c,0xbf78bf80,0x3e79bd49,
0xbd493e79,0xbf80bf78,0xbf2cbf5c,0x3f3e3f04,0xbf18beac,0xbf4ebf71,0xbe16bedb,0x3f7d3f67,0x3f553f7b,0xbf0ebe48,0xbf55bf7b,0x3f0e3e48,
0x3e483f0e,0xbf7bbf55,0xbe48bf0e,0x3f7b3f55,0xbf0ebe48,0xbf55bf7b,0x3f0e3e48,0x3f553f7b,0xbf7bbf55,0xbe48bf0e,0x3f7b3f55,0x3e483f0e,
0x3f3e3f78,0xbf2cbe79,0xbd49bf04,0x3f803f5c,0xbe163eac,0xbf7dbf71,0x3f4e3edb,0x3f183f67,0xbf67bf18,0xbedbbf4e,0x3f713f7d,0xbeac3e16,
0xbf5cbf80,0x3f043d49,0x3e793f2c,0xbf78bf3e,0x3f223f75,0xbf46be95,0x3f463e95,0x3f223f75,0xbef13dc9,0xbf62bf7f,0x3f623f7f,0xbef13dc9,
0xbf7fbf62,0x3dc9bef1,0xbdc93ef1,0xbf7fbf62,0xbe95bf46,0x3f753f22,0xbf75bf22,0xbe95bf46,0x3f043f71,0xbf5cbeac,0x3f783f67,0xbe793edb,
0xbf3ebe16,0xbf2cbf7d,0xbd493f18,0xbf80bf4e,0xbf4ebf80,0x3f18bd49,0xbf7dbf2c,0xbe16bf3e,0x3edbbe79,0x3f673f78,0xbeacbf5c,0x3f713f04,
0x3ec43f6d,0xbf6dbec4,0x3ec43f6d,0xbf6dbec4,0xbf6dbec4,0xbec4bf6d,0xbf6dbec4,0xbec4bf6d,0xbec4bf6d,0x3f6d3ec4,0xbec4bf6d,0x3f6d3ec4,
0x3f6d3ec4,0x3ec43f6d,0x3f6d3ec4,0x3ec43f6d,0x3e793f67,0xbf78bedb,0xbf043eac,0xbf5cbf71,0xbf80bf18,0xbd49bf4e,0xbf3ebf7d,0x3f2cbe16,
0x3e16bf2c,0x3f7d3f3e,0x3f4e3d49,0x3f183f80,0x3f713f5c,0xbeac3f04,0x3edb3f78,0xbf67be79,0x3dc93f62,0xbf7fbef1,0xbf7fbef1,0xbdc9bf62,
0xbf75bf46,0x3e95bf22,0x3e95bf22,0x3f753f46,0x3f22be95,0x3f463f75,0x3f463f75,0xbf223e95,0x3ef13f7f,0xbf62bdc9,0xbf62bdc9,0xbef1bf7f,
0xbd493f5c,0xbf80bf04,0xbf2cbf78,0x3f3ebe79,0xbf4ebf67,0x3f18bedb,0x3f7d3eac,0x3e163f71,0x3f713e16,0x3eac3f7d,0xbedb3f18,0xbf67bf4e,
0xbe793f3e,0xbf78bf2c,0xbf04bf80,0x3f5cbd49,0xbe483f55,0xbf7bbf0e,0x3e48bf55,0x3f7b3f0e,0xbf0ebf7b,0x3f55be48,0x3f0e3f7b,0xbf553e48,
0x3f7b3f0e,0xbe483f55,0xbf7bbf0e,0x3e48bf55,0xbf553e48,0xbf0ebf7b,0x3f55be48,0x3f0e3f7b,0xbeac3f4e,0xbf71bf18,0x3f67be16,0x3edb3f7d,
0xbe79bf80,0x3f783d49,0xbf043f2c,0xbf5cbf3e,0x3f3e3f5c,0xbf2c3f04,0xbd49bf78,0x3f803e79,0xbf7dbedb,0x3e16bf67,0x3f183f71,0xbf4e3eac,
0xbef13f46,0xbf62bf22,0x3f623f22,0xbef13f46,0x3dc9bf75,0x3f7f3e95,0xbf7fbe95,0x3dc9bf75,0x3e953f7f,0xbf753dc9,0x3f75bdc9,0x3e953f7f,
0xbf22bf62,0x3f46bef1,0xbf463ef1,0xbf22bf62,0xbf183f3e,0xbf4ebf2c,0x3e163f80,0xbf7d3d49,0x3edbbf5c,0x3f673f04,0xbeacbf78,0x3f71be79,
0xbe793f71,0xbf78beac,0x3f043f67,0xbf5c3edb,0x3d49bf7d,0x3f803e16,0xbf2cbf4e,0x3f3ebf18,0xbf353f35,0xbf35bf35,0xbf353f35,0xbf35bf35,
0x3f35bf35,0x3f353f35,0x3f35bf35,0x3f353f35,0xbf353f35,0xbf35bf35,0xbf353f35,0xbf35bf35,0x3f35bf35,0x3f353f35,0x3f35bf35,0x3f353f35,
0xbf4e3f2c,0xbf18bf3e,0xbf7dbd49,0x3e16bf80,0x3f67bf04,0x3edb3f5c,0x3f713e79,0xbeac3f78,0xbf783eac,0xbe79bf71,0xbf5cbedb,0x3f04bf67,
0x3f80be16,0x3d493f7d,0x3f3e3f18,0xbf2c3f4e,0xbf623f22,0xbef1bf46,0xbef1bf46,0x3f62bf22,0x3f7fbe95,0x3dc93f75,0x3dc93f75,0xbf7f3e95,
0xbf75bdc9,0x3e95bf7f,0x3e95bf7f,0x3f753dc9,0x3f463ef1,0xbf223f62,0xbf223f62,0xbf46bef1,0xbf713f18,0xbeacbf4e,0x3edbbf7d,0x3f673e16,
0x3f78bd49,0xbe793f80,0xbf5c3f3e,0xbf04bf2c,0xbf2cbf04,0x3f3ebf5c,0x3f80be79,0xbd493f78,0x3e163f67,0xbf7d3edb,0xbf4ebeac,0x3f18bf71,
0xbf7b3f0e,0xbe48bf55,0x3f7bbf0e,0x3e483f55,0x3f553e48,0xbf0e3f7b,0xbf55be48,0x3f0ebf7b,0xbe48bf55,0x3f7bbf0e,0x3e483f55,0xbf7b3f0e,
0xbf0e3f7b,0xbf55be48,0x3f0ebf7b,0x3f553e48,0xbf803f04,0xbd49bf5c,0x3f3e3e79,0xbf2c3f78,0x3f183edb,0xbf4e3f67,0x3e16bf71,0x3f7dbeac,
0x3eacbf7d,0x3f71be16,0xbf673f4e,0xbedbbf18,0xbf783f2c,0xbe79bf3e,0x3f5c3d49,0xbf043f80,0xbf7f3ef1,0x3dc9bf62,0xbdc93f62,0xbf7f3ef1,
0x3e953f22,0xbf753f46,0x3f75bf46,0x3e953f22,0x3f46bf75,0x3f223e95,0xbf22be95,0x3f46bf75,0xbf623dc9,0x3ef1bf7f,0xbef13f7f,0xbf623dc9,
0xbf783edb,0x3e79bf67,0xbf5c3f71,0xbf04beac,0xbd493f4e,0xbf803f18,0x3f2c3e16,0xbf3e3f7d,0x3f7dbf3e,0x3e163f2c,0x3f18bf80,0x3f4ebd49,
0xbeacbf04,0x3f71bf5c,0xbf673e79,0x3edbbf78,0xbf6d3ec4,0x3ec4bf6d,0xbf6d3ec4,0x3ec4bf6d,0xbec43f6d,0xbf6d3ec4,0xbec43f6d,0xbf6d3ec4,
0x3f6dbec4,0xbec43f6d,0x3f6dbec4,0xbec43f6d,0x3ec4bf6d,0x3f6dbec4,0x3ec4bf6d,0x3f6dbec4,0xbf5c3eac,0x3f04bf71,0xbe79bedb,0x3f78bf67,
0xbf2c3f7d,0xbf3e3e16,0xbf803f4e,0xbd49bf18,0x3f183d49,0xbf4e3f80,0xbe163f3e,0xbf7d3f2c,0x3f67bf78,0x3edb3e79,0x3f71bf04,0xbeac3f5c,
0xbf463e95,0x3f22bf75,0x3f22bf75,0x3f46be95,0xbf623f7f,0xbef1bdc9,0xbef1bdc9,0x3f62bf7f,0x3dc93ef1,0xbf7f3f62,0xbf7f3f62,0xbdc9bef1,
0x3f75bf22,0xbe953f46,0xbe953f46,0xbf753f22,0xbf2c3e79,0x3f3ebf78,0x3f80bf5c,0xbd493f04,0xbf7d3f71,0xbe16beac,0x3f18bf67,0x3f4ebedb,
0xbedb3f4e,0xbf673f18,0xbeacbe16,0x3f71bf7d,0x3f04bd49,0xbf5c3f80,0xbf783f3e,0x3e79bf2c,0xbf0e3e48,0x3f55bf7b,0x3f0ebe48,0xbf553f7b,
0xbf7b3f55,0x3e48bf0e,0x3f7bbf55,0xbe483f0e,0xbf553f7b,0xbf0e3e48,0x3f55bf7b,0x3f0ebe48,0xbe483f0e,0xbf7b3f55,0x3e48bf0e,0x3f7bbf55,
0xbedb3e16,0x3f67bf7d,0xbeac3f18,0xbf713f4e,0xbf5c3f2c,0x3f04bf3e,0x3e793d49,0xbf783f80,0xbf803f78,0xbd49be79,0x3f3ebf04,0xbf2c3f5c,
0xbf4e3f71,0xbf183eac,0x3f7dbf67,0xbe163edb,0xbe953dc9,0x3f75bf7f,0xbf753f7f,0xbe953dc9,0xbf223ef1,0x3f46bf62,0xbf463f62,0xbf223ef1,
0xbf623f46,0x3ef1bf22,0xbef13f22,0xbf623f46,0xbf7f3f75,0x3dc9be95,0xbdc93e95,0xbf7f3f75,0xbe163d49,0x3f7dbf80,0xbf4e3f3e,0x3f18bf2c,
0xbeac3e79,0x3f71bf78,0xbf673f5c,0x3edbbf04,0xbf043edb,0x3f5cbf67,0xbf783f71,0x3e79beac,0xbf2c3f18,0x3f3ebf4e,0xbf803f7d,0x3d49be16,
0x3f803f80,0xbf803f80,0x3f803f80,0xbf803f80,0x3f803f80,0xbf803f80,0x3f803f80,0xbf803f80,0x3f803f80,0xbf803f80,0x3f803f80,0xbf803f80,
0x3f803f80,0xbf803f80,0x3f803f80,0xbf803f80,0xbe16bd49,0xbf7dbf80,0xbf4ebf3e,0xbf18bf2c,0xbeacbe79,0xbf71bf78,0xbf67bf5c,0xbedbbf04,
0xbf04bedb,0xbf5cbf67,0xbf78bf71,0xbe79beac,0xbf2cbf18,0xbf3ebf4e,0xbf80bf7d,0xbd49be16,0xbf75bf7f,0x3e953dc9,0x3e953dc9,0x3f753f7f,
0xbf46bf62,0x3f223ef1,0x3f223ef1,0x3f463f62,0xbef1bf22,0x3f623f46,0x3f623f46,0x3ef13f22,0xbdc9be95,0x3f7f3f75,0x3f7f3f75,0x3dc93e95,
0x3edb3e16,0x3f673f7d,0x3eac3f18,0xbf71bf4e,0x3f5c3f2c,0x3f043f3e,0xbe793d49,0xbf78bf80,0x3f803f78,0xbd493e79,0xbf3ebf04,0xbf2cbf5c,
0x3f4e3f71,0xbf18beac,0xbf7dbf67,0xbe16bedb,0x3f553f7b,0xbf0ebe48,0xbf55bf7b,0x3f0e3e48,0x3e483f0e,0xbf7bbf55,0xbe48bf0e,0x3f7b3f55,
0xbf0ebe48,0xbf55bf7b,0x3f0e3e48,0x3f553f7b,0xbf7bbf55,0xbe48bf0e,0x3f7b3f55,0x3e483f0e,0xbf2cbe79,0xbf3ebf78,0x3f803f5c,0x3d493f04,
0xbf7dbf71,0x3e16beac,0x3f183f67,0xbf4ebedb,0xbedbbf4e,0x3f673f18,0xbeac3e16,0xbf71bf7d,0x3f043d49,0x3f5c3f80,0xbf78bf3e,0xbe79bf2c,
0xbf22bf75,0x3f463e95,0xbf46be95,0xbf22bf75,0x3ef1bdc9,0x3f623f7f,0xbf62bf7f,0x3ef1bdc9,0x3f7f3f62,0xbdc93ef1,0x3dc9bef1,0x3f7f3f62,
0x3e953f46,0xbf75bf22,0x3f753f22,0x3e953f46,0x3f5c3eac,0x3f043f71,0x3e79bedb,0x3f783f67,0x3f2c3f7d,0xbf3ebe16,0x3f803f4e,0xbd493f18,
0xbf183d49,0xbf4ebf80,0x3e163f3e,0xbf7dbf2c,0xbf67bf78,0x3edbbe79,0xbf71bf04,0xbeacbf5c,0x3ec43f6d,0xbf6dbec4,0x3ec43f6d,0xbf6dbec4,
0xbf6dbec4,0xbec4bf6d,0xbf6dbec4,0xbec4bf6d,0xbec4bf6d,0x3f6d3ec4,0xbec4bf6d,0x3f6d3ec4,0x3f6d3ec4,0x3ec43f6d,0x3f6d3ec4,0x3ec43f6d,
0xbf78bedb,0xbe79bf67,0xbf5cbf71,0x3f04beac,0xbd49bf4e,0x3f803f18,0x3f2cbe16,0x3f3e3f7d,0x3f7d3f3e,0xbe163f2c,0x3f183f80,0xbf4ebd49,
0xbeac3f04,0xbf71bf5c,0xbf67be79,0xbedbbf78,0xbdc9bf62,0x3f7f3ef1,0x3f7f3ef1,0x3dc93f62,0x3f753f46,0xbe953f22,0xbe953f22,0xbf75bf46,
0xbf223e95,0xbf46bf75,0xbf46bf75,0x3f22be95,0xbef1bf7f,0x3f623dc9,0x3f623dc9,0x3ef13f7f,0x3f803f04,0xbd493f5c,0xbf3e3e79,0xbf2cbf78,
0xbf183edb,0xbf4ebf67,0xbe16bf71,0x3f7d3eac,0xbeacbf7d,0x3f713e16,0x3f673f4e,0xbedb3f18,0x3f783f2c,0xbe793f3e,0xbf5c3d49,0xbf04bf80,
0xbe483f55,0xbf7bbf0e,0x3e48bf55,0x3f7b3f0e,0xbf0ebf7b,0x3f55be48,0x3f0e3f7b,0xbf553e48,0x3f7b3f0e,0xbe483f55,0xbf7bbf0e,0x3e48bf55,
0xbf553e48,0xbf0ebf7b,0x3f55be48,0x3f0e3f7b,0xbf71bf18,0x3eacbf4e,0x3edb3f7d,0xbf673e16,0x3f783d49,0x3e793f80,0xbf5cbf3e,0x3f04bf2c,
0xbf2c3f04,0xbf3ebf5c,0x3f803e79,0x3d493f78,0x3e16bf67,0x3f7d3edb,0xbf4e3eac,0xbf18bf71,0x3ef1bf46,0x3f623f22,0xbf62bf22,0x3ef1bf46,
0xbdc93f75,0xbf7fbe95,0x3f7f3e95,0xbdc93f75,0xbe95bf7f,0x3f75bdc9,0xbf753dc9,0xbe95bf7f,0x3f223f62,0xbf463ef1,0x3f46bef1,0x3f223f62,
0x3f4e3f2c,0xbf183f3e,0x3f7dbd49,0x3e163f80,0xbf67bf04,0x3edbbf5c,0xbf713e79,0xbeacbf78,0x3f783eac,0xbe793f71,0x3f5cbedb,0x3f043f67,
0xbf80be16,0x3d49bf7d,0xbf3e3f18,0xbf2cbf4e,0xbf353f35,0xbf35bf35,0xbf353f35,0xbf35bf35,0x3f35bf35,0x3f353f35,0x3f35bf35,0x3f353f35,
0xbf353f35,0xbf35bf35,0xbf353f35,0xbf35bf35,0x3f35bf35,0x3f353f35,0x3f35bf35,0x3f353f35,0xbf18bf3e,0x3f4ebf2c,0x3e16bf80,0x3f7d3d49,
0x3edb3f5c,0xbf673f04,0xbeac3f78,0xbf71be79,0xbe79bf71,0x3f78beac,0x3f04bf67,0x3f5c3edb,0x3d493f7d,0xbf803e16,0xbf2c3f4e,0xbf3ebf18,
0x3f62bf22,0x3ef13f46,0x3ef13f46,0xbf623f22,0xbf7f3e95,0xbdc9bf75,0xbdc9bf75,0x3f7fbe95,0x3f753dc9,0xbe953f7f,0xbe953f7f,0xbf75bdc9,
0xbf46bef1,0x3f22bf62,0x3f22bf62,0x3f463ef1,0x3eac3f4e,0xbf713f18,0xbf67be16,0x3edbbf7d,0x3e79bf80,0x3f78bd49,0x3f043f2c,0xbf5c3f3e,
0xbf3e3f5c,0xbf2cbf04,0x3d49bf78,0x3f80be79,0x3f7dbedb,0x3e163f67,0xbf183f71,0xbf4ebeac,0xbf7b3f0e,0xbe48bf55,0x3f7bbf0e,0x3e483f55,
0x3f553e48,0xbf0e3f7b,0xbf55be48,0x3f0ebf7b,0xbe48bf55,0x3f7bbf0e,0x3e483f55,0xbf7b3f0e,0xbf0e3f7b,0xbf55be48,0x3f0ebf7b,0x3f553e48,
0xbd49bf5c,0x3f80bf04,0xbf2c3f78,0xbf3ebe79,0xbf4e3f67,0xbf18bedb,0x3f7dbeac,0xbe163f71,0x3f71be16,0xbeac3f7d,0xbedbbf18,0x3f67bf4e,
0xbe79bf3e,0x3f78bf2c,0xbf043f80,0xbf5cbd49,0x3f7fbef1,0xbdc93f62,0x3dc9bf62,0x3f7fbef1,0xbe95bf22,0x3f75bf46,0xbf753f46,0xbe95bf22,
0xbf463f75,0xbf22be95,0x3f223e95,0xbf463f75,0x3f62bdc9,0xbef13f7f,0x3ef1bf7f,0x3f62bdc9,0xbe793f67,0xbf783edb,0x3f043eac,0xbf5c3f71,
0x3f80bf18,0xbd493f4e,0x3f3ebf7d,0x3f2c3e16,0xbe16bf2c,0x3f7dbf3e,0xbf4e3d49,0x3f18bf80,0xbf713f5c,0xbeacbf04,0xbedb3f78,0xbf673e79,
0xbf6d3ec4,0x3ec4bf6d,0xbf6d3ec4,0x3ec4bf6d,0xbec43f6d,0xbf6d3ec4,0xbec43f6d,0xbf6d3ec4,0x3f6dbec4,0xbec43f6d,0x3f6dbec4,0xbec43f6d,
0x3ec4bf6d,0x3f6dbec4,0x3ec4bf6d,0x3f6dbec4,0x3f04bf71,0x3f5cbeac,0x3f78bf67,0x3e793edb,0xbf3e3e16,0x3f2cbf7d,0xbd49bf18,0x3f80bf4e,
0xbf4e3f80,0xbf18bd49,0xbf7d3f2c,0x3e16bf3e,0x3edb3e79,0xbf673f78,0xbeac3f5c,0xbf713f04,0x3f46be95,0xbf223f75,0xbf223f75,0xbf463e95,
0x3f62bf7f,0x3ef13dc9,0x3ef13dc9,0xbf623f7f,0xbdc9bef1,0x3f7fbf62,0x3f7fbf62,0x3dc93ef1,0xbf753f22,0x3e95bf46,0x3e95bf46,0x3f75bf22,
0xbf3e3f78,0xbf2c3e79,0x3d49bf04,0x3f80bf5c,0x3e163eac,0xbf7d3f71,0xbf4e3edb,0x3f18bf67,0x3f67bf18,0xbedb3f4e,0xbf713f7d,0xbeacbe16,
0x3f5cbf80,0x3f04bd49,0xbe793f2c,0xbf783f3e,0xbf0e3e48,0x3f55bf7b,0x3f0ebe48,0xbf553f7b,0xbf7b3f55,0x3e48bf0e,0x3f7bbf55,0xbe483f0e,
0xbf553f7b,0xbf0e3e48,0x3f55bf7b,0x3f0ebe48,0xbe483f0e,0xbf7b3f55,0x3e48bf0e,0x3f7bbf55,0x3f67bf7d,0x3edbbe16,0xbf713f4e,0x3eacbf18,
0x3f04bf3e,0x3f5cbf2c,0xbf783f80,0xbe79bd49,0xbd49be79,0x3f80bf78,0xbf2c3f5c,0xbf3e3f04,0xbf183eac,0x3f4ebf71,0xbe163edb,0xbf7d3f67,
0x3e95bdc9,0xbf753f7f,0x3f75bf7f,0x3e95bdc9,0x3f22bef1,0xbf463f62,0x3f46bf62,0x3f22bef1,0x3f62bf46,0xbef13f22,0x3ef1bf22,0x3f62bf46,
0x3f7fbf75,0xbdc93e95,0x3dc9be95,0x3f7fbf75,0xbf7d3f80,0xbe163d49,0xbf183f2c,0xbf4e3f3e,0xbf713f78,0xbeac3e79,0xbedb3f04,0xbf673f5c,
0xbf5c3f67,0xbf043edb,0xbe793eac,0xbf783f71,0xbf3e3f4e,0xbf2c3f18,0xbd493e16,0xbf803f7d,0x3f803f80,0xbf803f80,0x3f803f80,0xbf803f80,
0x3f803f80,0xbf803f80,0x3f803f80,0xbf803f80,0x3f803f80,0xbf803f80,0x3f803f80,0xbf803f80,0x3f803f80,0xbf803f80,0x3f803f80,0xbf803f80,
0xbf7dbf80,0x3e163d49,0xbf18bf2c,0x3f4e3f3e,0xbf71bf78,0x3eac3e79,0xbedbbf04,0x3f673f5c,0xbf5cbf67,0x3f043edb,0xbe79beac,0x3f783f71,
0xbf3ebf4e,0x3f2c3f18,0xbd49be16,0x3f803f7d,0x3f753f7f,0xbe95bdc9,0xbe95bdc9,0xbf75bf7f,0x3f463f62,0xbf22bef1,0xbf22bef1,0xbf46bf62,
0x3ef13f22,0xbf62bf46,0xbf62bf46,0xbef1bf22,0x3dc93e95,0xbf7fbf75,0xbf7fbf75,0xbdc9be95,0xbf67bf7d,0x3edb3e16,0x3f713f4e,0x3eac3f18,
0xbf04bf3e,0x3f5c3f2c,0x3f783f80,0xbe793d49,0x3d49be79,0x3f803f78,0x3f2c3f5c,0xbf3ebf04,0x3f183eac,0x3f4e3f71,0x3e163edb,0xbf7dbf67,
0x3f553f7b,0xbf0ebe48,0xbf55bf7b,0x3f0e3e48,0x3e483f0e,0xbf7bbf55,0xbe48bf0e,0x3f7b3f55,0xbf0ebe48,0xbf55bf7b,0x3f0e3e48,0x3f553f7b,
0xbf7bbf55,0xbe48bf0e,0x3f7b3f55,0x3e483f0e,0xbf3ebf78,0x3f2c3e79,0x3d493f04,0xbf80bf5c,0x3e16beac,0x3f7d3f71,0xbf4ebedb,0xbf18bf67,
0x3f673f18,0x3edb3f4e,0xbf71bf7d,0x3eacbe16,0x3f5c3f80,0xbf04bd49,0xbe79bf2c,0x3f783f3e,0x3f223f75,0xbf46be95,0x3f463e95,0x3f223f75,
0xbef13dc9,0xbf62bf7f,0x3f623f7f,0xbef13dc9,0xbf7fbf62,0x3dc9bef1,0xbdc93ef1,0xbf7fbf62,0xbe95bf46,0x3f753f22,0xbf75bf22,0xbe95bf46,
0xbf04bf71,0x3f5c3eac,0xbf78bf67,0x3e79bedb,0x3f3e3e16,0x3f2c3f7d,0x3d49bf18,0x3f803f4e,0x3f4e3f80,0xbf183d49,0x3f7d3f2c,0x3e163f3e,
0xbedb3e79,0xbf67bf78,0x3eac3f5c,0xbf71bf04,0x3ec43f6d,0xbf6dbec4,0x3ec43f6d,0xbf6dbec4,0xbf6dbec4,0xbec4bf6d,0xbf6dbec4,0xbec4bf6d,
0xbec4bf6d,0x3f6d3ec4,0xbec4bf6d,0x3f6d3ec4,0x3f6d3ec4,0x3ec43f6d,0x3f6d3ec4,0x3ec43f6d,0xbe79bf67,0x3f783edb,0x3f04beac,0x3f5c3f71,
0x3f803f18,0x3d493f4e,0x3f3e3f7d,0xbf2c3e16,0xbe163f2c,0xbf7dbf3e,0xbf4ebd49,0xbf18bf80,0xbf71bf5c,0x3eacbf04,0xbedbbf78,0x3f673e79,
0x3dc93f62,0xbf7fbef1,0xbf7fbef1,0xbdc9bf62,0xbf75bf46,0x3e95bf22,0x3e95bf22,0x3f753f46,0x3f22be95,0x3f463f75,0x3f463f75,0xbf223e95,
0x3ef13f7f,0xbf62bdc9,0xbf62bdc9,0xbef1bf7f,0x3d49bf5c,0x3f803f04,0x3f2c3f78,0xbf3e3e79,0x3f4e3f67,0xbf183edb,0xbf7dbeac,0xbe16bf71,
0xbf71be16,0xbeacbf7d,0x3edbbf18,0x3f673f4e,0x3e79bf3e,0x3f783f2c,0x3f043f80,0xbf5c3d49,0xbe483f55,0xbf7bbf0e,0x3e48bf55,0x3f7b3f0e,
0xbf0ebf7b,0x3f55be48,0x3f0e3f7b,0xbf553e48,0x3f7b3f0e,0xbe483f55,0xbf7bbf0e,0x3e48bf55,0xbf553e48,0xbf0ebf7b,0x3f55be48,0x3f0e3f7b,
0x3eacbf4e,0x3f713f18,0xbf673e16,0xbedbbf7d,0x3e793f80,0xbf78bd49,0x3f04bf2c,0x3f5c3f3e,0xbf3ebf5c,0x3f2cbf04,0x3d493f78,0xbf80be79,
0x3f7d3edb,0xbe163f67,0xbf18bf71,0x3f4ebeac,0xbef13f46,0xbf62bf22,0x3f623f22,0xbef13f46,0x3dc9bf75,0x3f7f3e95,0xbf7fbe95,0x3dc9bf75,
0x3e953f7f,0xbf753dc9,0x3f75bdc9,0x3e953f7f,0xbf22bf62,0x3f46bef1,0xbf463ef1,0xbf22bf62,0x3f18bf3e,0x3f4e3f2c,0xbe16bf80,0x3f7dbd49,
0xbedb3f5c,0xbf67bf04,0x3eac3f78,0xbf713e79,0x3e79bf71,0x3f783eac,0xbf04bf67,0x3f5cbedb,0xbd493f7d,0xbf80be16,0x3f2c3f4e,0xbf3e3f18,
0xbf353f35,0xbf35bf35,0xbf353f35,0xbf35bf35,0x3f35bf35,0x3f353f35,0x3f35bf35,0x3f353f35,0xbf353f35,0xbf35bf35,0xbf353f35,0xbf35bf35,
0x3f35bf35,0x3f353f35,0x3f35bf35,0x3f353f35,0x3f4ebf2c,0x3f183f3e,0x3f7d3d49,0xbe163f80,0xbf673f04,0xbedbbf5c,0xbf71be79,0x3eacbf78,
0x3f78beac,0x3e793f71,0x3f5c3edb,0xbf043f67,0xbf803e16,0xbd49bf7d,0xbf3ebf18,0x3f2cbf4e,0xbf623f22,0xbef1bf46,0xbef1bf46,0x3f62bf22,
0x3f7fbe95,0x3dc93f75,0x3dc93f75,0xbf7f3e95,0xbf75bdc9,0x3e95bf7f,0x3e95bf7f,0x3f753dc9,0x3f463ef1,0xbf223f62,0xbf223f62,0xbf46bef1,
0x3f71bf18,0x3eac3f4e,0xbedb3f7d,0xbf67be16,0xbf783d49,0x3e79bf80,0x3f5cbf3e,0x3f043f2c,0x3f2c3f04,0xbf3e3f5c,0xbf803e79,0x3d49bf78,
0xbe16bf67,0x3f7dbedb,0x3f4e3eac,0xbf183f71,0xbf7b3f0e,0xbe48bf55,0x3f7bbf0e,0x3e483f55,0x3f553e48,0xbf0e3f7b,0xbf55be48,0x3f0ebf7b,
0xbe48bf55,0x3f7bbf0e,0x3e483f55,0xbf7b3f0e,0xbf0e3f7b,0xbf55be48,0x3f0ebf7b,0x3f553e48,0x3f80bf04,0x3d493f5c,0xbf3ebe79,0x3f2cbf78,
0xbf18bedb,0x3f4ebf67,0xbe163f71,0xbf7d3eac,0xbeac3f7d,0xbf713e16,0x3f67bf4e,0x3edb3f18,0x3f78bf2c,0x3e793f3e,0xbf5cbd49,0x3f04bf80,
0xbf7f3ef1,0x3dc9bf62,0xbdc93f62,0xbf7f3ef1,0x3e953f22,0xbf753f46,0x3f75bf46,0x3e953f22,0x3f46bf75,0x3f223e95,0xbf22be95,0x3f46bf75,
0xbf623dc9,0x3ef1bf7f,0xbef13f7f,0xbf623dc9,0x3f78bedb,0xbe793f67,0x3f5cbf71,0x3f043eac,0x3d49bf4e,0x3f80bf18,0xbf2cbe16,0x3f3ebf7d,
0xbf7d3f3e,0xbe16bf2c,0xbf183f80,0xbf4e3d49,0x3eac3f04,0xbf713f5c,0x3f67be79,0xbedb3f78,0xbf6d3ec4,0x3ec4bf6d,0xbf6d3ec4,0x3ec4bf6d,
0xbec43f6d,0xbf6d3ec4,0xbec43f6d,0xbf6d3ec4,0x3f6dbec4,0xbec43f6d,0x3f6dbec4,0xbec43f6d,0x3ec4bf6d,0x3f6dbec4,0x3ec4bf6d,0x3f6dbec4,
0x3f5cbeac,0xbf043f71,0x3e793edb,0xbf783f67,0x3f2cbf7d,0x3f3ebe16,0x3f80bf4e,0x3d493f18,0xbf18bd49,0x3f4ebf80,0x3e16bf3e,0x3f7dbf2c,
0xbf673f78,0xbedbbe79,0xbf713f04,0x3eacbf5c,0xbf463e95,0x3f22bf75,0x3f22bf75,0x3f46be95,0xbf623f7f,0xbef1bdc9,0xbef1bdc9,0x3f62bf7f,
0x3dc93ef1,0xbf7f3f62,0xbf7f3f62,0xbdc9bef1,0x3f75bf22,0xbe953f46,0xbe953f46,0xbf753f22,0x3f2cbe79,0xbf3e3f78,0xbf803f5c,0x3d49bf04,
0x3f7dbf71,0x3e163eac,0xbf183f67,0xbf4e3edb,0x3edbbf4e,0x3f67bf18,0x3eac3e16,0xbf713f7d,0xbf043d49,0x3f5cbf80,0x3f78bf3e,0xbe793f2c,
0xbf0e3e48,0x3f55bf7b,0x3f0ebe48,0xbf553f7b,0xbf7b3f55,0x3e48bf0e,0x3f7bbf55,0xbe483f0e,0xbf553f7b,0xbf0e3e48,0x3f55bf7b,0x3f0ebe48,
0xbe483f0e,0xbf7b3f55,0x3e48bf0e,0x3f7bbf55,0x3edbbe16,0xbf673f7d,0x3eacbf18,0x3f71bf4e,0x3f5cbf2c,0xbf043f3e,0xbe79bd49,0x3f78bf80,
0x3f80bf78,0x3d493e79,0xbf3e3f04,0x3f2cbf5c,0x3f4ebf71,0x3f18beac,0xbf7d3f67,0x3e16bedb,0xbe953dc9,0x3f75bf7f,0xbf753f7f,0xbe953dc9,
0xbf223ef1,0x3f46bf62,0xbf463f62,0xbf223ef1,0xbf623f46,0x3ef1bf22,0xbef13f22,0xbf623f46,0xbf7f3f75,0x3dc9be95,0xbdc93e95,0xbf7f3f75,
0x3e16bd49,0xbf7d3f80,0x3f4ebf3e,0xbf183f2c,0x3eacbe79,0xbf713f78,0x3f67bf5c,0xbedb3f04,0x3f04bedb,0xbf5c3f67,0x3f78bf71,0xbe793eac,
0x3f2cbf18,0xbf3e3f4e,0x3f80bf7d,0xbd493e16,0x3f803f80,0xbf803f80,0x3f803f80,0xbf803f80,0x3f803f80,0xbf803f80,0x3f803f80,0xbf803f80,
0x3f803f80,0xbf803f80,0x3f803f80,0xbf803f80,0x3f803f80,0xbf803f80,0x3f803f80,0xbf803f80,0x3e163d49,0x3f7d3f80,0x3f4e3f3e,0x3f183f2c,
0x3eac3e79,0x3f713f78,0x3f673f5c,0x3edb3f04,0x3f043edb,0x3f5c3f67,0x3f783f71,0x3e793eac,0x3f2c3f18,0x3f3e3f4e,0x3f803f7d,0x3d493e16,
0xbf75bf7f,0x3e953dc9,0x3e953dc9,0x3f753f7f,0xbf46bf62,0x3f223ef1,0x3f223ef1,0x3f463f62,0xbef1bf22,0x3f623f46,0x3f623f46,0x3ef13f22,
0xbdc9be95,0x3f7f3f75,0x3f7f3f75,0x3dc93e95,0xbedbbe16,0xbf67bf7d,0xbeacbf18,0x3f713f4e,0xbf5cbf2c,0xbf04bf3e,0x3e79bd49,0x3f783f80,
0xbf80bf78,0x3d49be79,0x3f3e3f04,0x3f2c3f5c,0xbf4ebf71,0x3f183eac,0x3f7d3f67,0x3e163edb,0x3f553f7b,0xbf0ebe48,0xbf55bf7b,0x3f0e3e48,
0x3e483f0e,0xbf7bbf55,0xbe48bf0e,0x3f7b3f55,0xbf0ebe48,0xbf55bf7b,0x3f0e3e48,0x3f553f7b,0xbf7bbf55,0xbe48bf0e,0x3f7b3f55,0x3e483f0e,
0x3f2c3e79,0x3f3e3f78,0xbf80bf5c,0xbd49bf04,0x3f7d3f71,0xbe163eac,0xbf18bf67,0x3f4e3edb,0x3edb3f4e,0xbf67bf18,0x3eacbe16,0x3f713f7d,
0xbf04bd49,0xbf5cbf80,0x3f783f3e,0x3e793f2c,0xbf22bf75,0x3f463e95,0xbf46be95,0xbf22bf75,0x3ef1bdc9,0x3f623f7f,0xbf62bf7f,0x3ef1bdc9,
0x3f7f3f62,0xbdc93ef1,0x3dc9bef1,0x3f7f3f62,0x3e953f46,0xbf75bf22,0x3f753f22,0x3e953f46,0xbf5cbeac,0xbf04bf71,0xbe793edb,0xbf78bf67,
0xbf2cbf7d,0x3f3e3e16,0xbf80bf4e,0x3d49bf18,0x3f18bd49,0x3f4e3f80,0xbe16bf3e,0x3f7d3f2c,0x3f673f78,0xbedb3e79,0x3f713f04,0x3eac3f5c,
0x3ec43f6d,0xbf6dbec4,0x3ec43f6d,0xbf6dbec4,0xbf6dbec4,0xbec4bf6d,0xbf6dbec4,0xbec4bf6d,0xbec4bf6d,0x3f6d3ec4,0xbec4bf6d,0x3f6d3ec4,
0x3f6d3ec4,0x3ec43f6d,0x3f6d3ec4,0x3ec43f6d,0x3f783edb,0x3e793f67,0x3f5c3f71,0xbf043eac,0x3d493f4e,0xbf80bf18,0xbf2c3e16,0xbf3ebf7d,
0xbf7dbf3e,0x3e16bf2c,0xbf18bf80,0x3f4e3d49,0x3eacbf04,0x3f713f5c,0x3f673e79,0x3edb3f78,0xbdc9bf62,0x3f7f3ef1,0x3f7f3ef1,0x3dc93f62,
0x3f753f46,0xbe953f22,0xbe953f22,0xbf75bf46,0xbf223e95,0xbf46bf75,0xbf46bf75,0x3f22be95,0xbef1bf7f,0x3f623dc9,0x3f623dc9,0x3ef13f7f,
0xbf80bf04,0x3d49bf5c,0x3f3ebe79,0x3f2c3f78,0x3f18bedb,0x3f4e3f67,0x3e163f71,0xbf7dbeac,0x3eac3f7d,0xbf71be16,0xbf67bf4e,0x3edbbf18,
0xbf78bf2c,0x3e79bf3e,0x3f5cbd49,0x3f043f80,0xbe483f55,0xbf7bbf0e,0x3e48bf55,0x3f7b3f0e,0xbf0ebf7b,0x3f55be48,0x3f0e3f7b,0xbf553e48,
0x3f7b3f0e,0xbe483f55,0xbf7bbf0e,0x3e48bf55,0xbf553e48,0xbf0ebf7b,0x3f55be48,0x3f0e3f7b,0x3f713f18,0xbeac3f4e,0xbedbbf7d,0x3f67be16,
0xbf78bd49,0xbe79bf80,0x3f5c3f3e,0xbf043f2c,0x3f2cbf04,0x3f3e3f5c,0xbf80be79,0xbd49bf78,0xbe163f67,0xbf7dbedb,0x3f4ebeac,0x3f183f71,
0x3ef1bf46,0x3f623f22,0xbf62bf22,0x3ef1bf46,0xbdc93f75,0xbf7fbe95,0x3f7f3e95,0xbdc93f75,0xbe95bf7f,0x3f75bdc9,0xbf753dc9,0xbe95bf7f,
0x3f223f62,0xbf463ef1,0x3f46bef1,0x3f223f62,0xbf4ebf2c,0x3f18bf3e,0xbf7d3d49,0xbe16bf80,0x3f673f04,0xbedb3f5c,0x3f71be79,0x3eac3f78,
0xbf78beac,0x3e79bf71,0xbf5c3edb,0xbf04bf67,0x3f803e16,0xbd493f7d,0x3f3ebf18,0x3f2c3f4e,0xbf353f35,0xbf35bf35,0xbf353f35,0xbf35bf35,
0x3f35bf35,0x3f353f35,0x3f35bf35,0x3f353f35,0xbf353f35,0xbf35bf35,0xbf353f35,0xbf35bf35,0x3f35bf35,0x3f353f35,0x3f35bf35,0x3f353f35,
0x3f183f3e,0xbf4e3f2c,0xbe163f80,0xbf7dbd49,0xbedbbf5c,0x3f67bf04,0x3eacbf78,0x3f713e79,0x3e793f71,0xbf783eac,0xbf043f67,0xbf5cbedb,
0xbd49bf7d,0x3f80be16,0x3f2cbf4e,0x3f3e3f18,0x3f62bf22,0x3ef13f46,0x3ef13f46,0xbf623f22,0xbf7f3e95,0xbdc9bf75,0xbdc9bf75,0x3f7fbe95,
0x3f753dc9,0xbe953f7f,0xbe953f7f,0xbf75bdc9,0xbf46bef1,0x3f22bf62,0x3f22bf62,0x3f463ef1,0xbeacbf4e,0x3f71bf18,0x3f673e16,0xbedb3f7d,
0xbe793f80,0xbf783d49,0xbf04bf2c,0x3f5cbf3e,0x3f3ebf5c,0x3f2c3f04,0xbd493f78,0xbf803e79,0xbf7d3edb,0xbe16bf67,0x3f18bf71,0x3f4e3eac,
0xbf7b3f0e,0xbe48bf55,0x3f7bbf0e,0x3e483f55,0x3f553e48,0xbf0e3f7b,0xbf55be48,0x3f0ebf7b,0xbe48bf55,0x3f7bbf0e,0x3e483f55,0xbf7b3f0e,
0xbf0e3f7b,0xbf55be48,0x3f0ebf7b,0x3f553e48,0x3d493f5c,0xbf803f04,0x3f2cbf78,0x3f3e3e79,0x3f4ebf67,0x3f183edb,0xbf7d3eac,0x3e16bf71,
0xbf713e16,0x3eacbf7d,0x3edb3f18,0xbf673f4e,0x3e793f3e,0xbf783f2c,0x3f04bf80,0x3f5c3d49,0x3f7fbef1,0xbdc93f62,0x3dc9bf62,0x3f7fbef1,
0xbe95bf22,0x3f75bf46,0xbf753f46,0xbe95bf22,0xbf463f75,0xbf22be95,0x3f223e95,0xbf463f75,0x3f62bdc9,0xbef13f7f,0x3ef1bf7f,0x3f62bdc9,
0x3e79bf67,0x3f78bedb,0xbf04beac,0x3f5cbf71,0xbf803f18,0x3d49bf4e,0xbf3e3f7d,0xbf2cbe16,0x3e163f2c,0xbf7d3f3e,0x3f4ebd49,0xbf183f80,
0x3f71bf5c,0x3eac3f04,0x3edbbf78,0x3f67be79,0xbf6d3ec4,0x3ec4bf6d,0xbf6d3ec4,0x3ec4bf6d,0xbec43f6d,0xbf6d3ec4,0xbec43f6d,0xbf6d3ec4,
0x3f6dbec4,0xbec43f6d,0x3f6dbec4,0xbec43f6d,0x3ec4bf6d,0x3f6dbec4,0x3ec4bf6d,0x3f6dbec4,0xbf043f71,0xbf5c3eac,0xbf783f67,0xbe79bedb,
0x3f3ebe16,0xbf2c3f7d,0x3d493f18,0xbf803f4e,0x3f4ebf80,0x3f183d49,0x3f7dbf2c,0xbe163f3e,0xbedbbe79,0x3f67bf78,0x3eacbf5c,0x3f71bf04,
0x3f46be95,0xbf223f75,0xbf223f75,0xbf463e95,0x3f62bf7f,0x3ef13dc9,0x3ef13dc9,0xbf623f7f,0xbdc9bef1,0x3f7fbf62,0x3f7fbf62,0x3dc93ef1,
0xbf753f22,0x3e95bf46,0x3e95bf46,0x3f75bf22,0x3f3ebf78,0x3f2cbe79,0xbd493f04,0xbf803f5c,0xbe16beac,0x3f7dbf71,0x3f4ebedb,0xbf183f67,
0xbf673f18,0x3edbbf4e,0x3f71bf7d,0x3eac3e16,0xbf5c3f80,0xbf043d49,0x3e79bf2c,0x3f78bf3e,0xbf0e3e48,0x3f55bf7b,0x3f0ebe48,0xbf553f7b,
0xbf7b3f55,0x3e48bf0e,0x3f7bbf55,0xbe483f0e,0xbf553f7b,0xbf0e3e48,0x3f55bf7b,0x3f0ebe48,0xbe483f0e,0xbf7b3f55,0x3e48bf0e,0x3f7bbf55,
0xbf673f7d,0xbedb3e16,0x3f71bf4e,0xbeac3f18,0xbf043f3e,0xbf5c3f2c,0x3f78bf80,0x3e793d49,0x3d493e79,0xbf803f78,0x3f2cbf5c,0x3f3ebf04,
0x3f18beac,0xbf4e3f71,0x3e16bedb,0x3f7dbf67,0x3e95bdc9,0xbf753f7f,0x3f75bf7f,0x3e95bdc9,0x3f22bef1,0xbf463f62,0x3f46bf62,0x3f22bef1,
0x3f62bf46,0xbef13f22,0x3ef1bf22,0x3f62bf46,0x3f7fbf75,0xbdc93e95,0x3dc9be95,0x3f7fbf75,0x3f7dbf80,0x3e16bd49,0x3f18bf2c,0x3f4ebf3e,
0x3f71bf78,0x3eacbe79,0x3edbbf04,0x3f67bf5c,0x3f5cbf67,0x3f04bedb,0x3e79beac,0x3f78bf71,0x3f3ebf4e,0x3f2cbf18,0x3d49be16,0x3f80bf7d,
0x3f803f80,0xbf353f35,0x3f803f80,0xbf353f35,0x3f803f80,0xbf353f35,0x3f803f80,0xbf353f35,0x3f803f80,0xbf353f35,0x3f803f80,0xbf353f35,
0x3f803f80,0xbf353f35,0x3f803f80,0xbf353f35,0x3f7c3f7f,0xbe2fbd97,0x3f133f27,0xbf51bf42,0x3f6f3f77,0xbeb8be89,0x3ecf3efc,0xbf6abf5f,
0x3f583f65,0xbf09bee6,0x3e603ea1,0xbf7abf73,0x3f393f4a,0xbf31bf1d,0x3cc93dfb,0xbf80bf7e,0x3f713f7d,0xbeacbe16,0xbeacbe16,0xbf71bf7d,
0x3f3e3f5c,0xbf2cbf04,0xbf2cbf04,0xbf3ebf5c,0x3edb3f18,0xbf67bf4e,0xbf67bf4e,0xbedbbf18,0x3d493e79,0xbf80bf78,0xbf80bf78,0xbd49be79,
0x3f5f3f7a,0xbefcbe60,0xbf77bf58,0xbe89bf09,0x3ee63f31,0xbf65bf39,0xbf73bf80,0x3ea13cc9,0xbdfb3e2f,0xbf7ebf7c,0xbf1dbf51,0x3f4a3f13,
0xbf27becf,0xbf42bf6a,0xbd97beb8,0x3f7f3f6f,0x3f463f75,0xbf22be95,0xbf46bf75,0x3f223e95,0x3dc93ef1,0xbf7fbf62,0xbdc9bef1,0x3f7f3f62,
0xbf22be95,0xbf46bf75,0x3f223e95,0x3f463f75,0xbf7fbf62,0xbdc9bef1,0x3f7f3f62,0x3dc93ef1,0x3f273f6f,0xbf42beb8,0x3d97becf,0x3f7f3f6a,
0xbe893e60,0xbf77bf7a,0x3f5f3f09,0x3efc3f58,0xbf73bf31,0xbea1bf39,0x3f653f80,0xbee63cc9,0xbf4abf7c,0x3f1d3e2f,0x3dfb3f13,0xbf7ebf51,
0x3f043f67,0xbf5cbedb,0x3f5c3edb,0x3f043f67,0xbf18bd49,0xbf4ebf80,0x3f4e3f80,0xbf18bd49,0xbf78bf71,0x3e79beac,0xbe793eac,0xbf78bf71,
0xbe16bf2c,0x3f7d3f3e,0xbf7dbf3e,0xbe16bf2c,0x3eb83f5f,0xbf6fbefc,0x3f6a3f77,0xbecf3e89,0xbf58bea1,0xbf09bf73,0xbe603ee6,0xbf7abf65,
0xbf31bf7e,0x3f393dfb,0xbf80bf4a,0x3cc9bf1d,0x3f13bd97,0x3f513f7f,0xbe2fbf42,0x3f7c3f27,0x3e483f55,0xbf7bbf0e,0x3e483f55,0xbf7bbf0e,
0xbf7bbf0e,0xbe48bf55,0xbf7bbf0e,0xbe48bf55,0xbe48bf55,0x3f7b3f0e,0xbe48bf55,0x3f7b3f0e,0x3f7b3f0e,0x3e483f55,0x3f7b3f0e,0x3e483f55,
0x3cc93f4a,0xbf80bf1d,0xbf313dfb,0xbf39bf7e,0xbf7cbf42,0x3e2fbf27,0xbf13bf7f,0x3f513d97,0x3eb8befc,0x3f6f3f5f,0x3f6a3e89,0x3ecf3f77,
0x3f583f73,0xbf093ea1,0x3e603f65,0xbf7abee6,0xbe163f3e,0xbf7dbf2c,0xbf7dbf2c,0x3e16bf3e,0xbf5cbf67,0x3f04bedb,0x3f04bedb,0x3f5c3f67,
0x3f4ebd49,0x3f183f80,0x3f183f80,0xbf4e3d49,0x3e793f71,0xbf78beac,0xbf78beac,0xbe79bf71,0xbea13f31,0xbf73bf39,0xbee6bf80,0x3f653cc9,
0xbf1dbf7c,0x3f4abe2f,0x3f7e3f13,0xbdfb3f51,0x3f7f3ecf,0x3d973f6a,0xbf273eb8,0xbf42bf6f,0xbefc3f09,0xbf5fbf58,0xbe89bf7a,0x3f773e60,
0xbef13f22,0xbf62bf46,0x3ef1bf22,0x3f623f46,0xbe95bf7f,0x3f753dc9,0x3e953f7f,0xbf75bdc9,0x3f623f46,0xbef13f22,0xbf62bf46,0x3ef1bf22,
0xbf75bdc9,0xbe95bf7f,0x3f753dc9,0x3e953f7f,0xbf1d3f13,0xbf4abf51,0x3f7e3e2f,0x3dfb3f7c,0x3d97bf6f,0x3f7f3eb8,0xbf423ecf,0xbf27bf6a,
0x3efc3f7a,0xbf5f3e60,0x3e89bf58,0x3f773f09,0xbf65bf31,0x3ee6bf39,0x3ea13f80,0xbf733cc9,0xbf3e3f04,0xbf2cbf5c,0x3f2c3f5c,0xbf3e3f04,
0x3edbbf4e,0x3f673f18,0xbf67bf18,0x3edbbf4e,0xbd493f78,0xbf80be79,0x3f803e79,0xbd493f78,0xbeacbf7d,0x3f71be16,0xbf713e16,0xbeacbf7d,
0xbf583ee6,0xbf09bf65,0xbe603f73,0xbf7abea1,0x3f39bf1d,0x3f313f4a,0x3cc9bf7e,0x3f803dfb,0xbf133f42,0xbf51bf27,0x3e2f3f7f,0xbf7c3d97,
0x3ecfbf5f,0x3f6a3efc,0xbeb8bf77,0x3f6fbe89,0xbf6d3ec4,0xbec4bf6d,0xbf6d3ec4,0xbec4bf6d,0x3f6dbec4,0x3ec43f6d,0x3f6dbec4,0x3ec43f6d,
0xbf6d3ec4,0xbec4bf6d,0xbf6d3ec4,0xbec4bf6d,0x3f6dbec4,0x3ec43f6d,0x3f6dbec4,0x3ec43f6d,0xbf7a3ea1,0xbe60bf73,0xbf58bee6,0x3f09bf65,
0x3f80bdfb,0x3cc93f7e,0x3f393f1d,0xbf313f4a,0xbf7cbd97,0x3e2fbf7f,0xbf13bf42,0x3f51bf27,0x3f6f3e89,0xbeb83f77,0x3ecf3f5f,0xbf6a3efc,
0xbf803e79,0xbd49bf78,0xbd49bf78,0x3f80be79,0x3f713e16,0xbeac3f7d,0xbeac3f7d,0xbf71be16,0xbf3ebf04,0x3f2cbf5c,0x3f2cbf5c,0x3f3e3f04,
0x3edb3f4e,0xbf673f18,0xbf673f18,0xbedbbf4e,0xbf7e3e2f,0x3dfbbf7c,0x3f4abf51,0x3f1d3f13,0x3f423ecf,0xbf273f6a,0xbf7f3eb8,0xbd97bf6f,
0xbe89bf58,0x3f77bf09,0x3f5f3e60,0xbefc3f7a,0xbea13f80,0xbf73bcc9,0xbee6bf39,0x3f65bf31,0xbf753dc9,0x3e95bf7f,0x3f75bdc9,0xbe953f7f,
0x3ef13f22,0xbf623f46,0xbef1bf22,0x3f62bf46,0x3e95bf7f,0x3f75bdc9,0xbe953f7f,0xbf753dc9,0xbf623f46,0xbef1bf22,0x3f62bf46,0x3ef13f22,
0xbf653cc9,0x3ee6bf80,0x3ea13f31,0xbf733f39,0x3dfb3f51,0xbf7e3f13,0x3f1dbf7c,0x3f4a3e2f,0x3f42bf6f,0x3f273eb8,0xbf7f3ecf,0x3d97bf6a,
0xbf773e60,0x3e89bf7a,0x3efc3f09,0xbf5f3f58,0xbf4ebd49,0x3f18bf80,0xbf183f80,0xbf4ebd49,0xbe793f71,0xbf783eac,0x3f78beac,0xbe793f71,
0x3f7dbf2c,0x3e163f3e,0xbe16bf3e,0x3f7dbf2c,0xbf04bedb,0x3f5cbf67,0xbf5c3f67,0xbf04bedb,0xbf31bdfb,0x3f39bf7e,0xbf803f1d,0x3cc9bf4a,
0xbf133f7f,0xbf513d97,0x3e2f3f27,0xbf7c3f42,0x3f6abe89,0xbecf3f77,0x3f6fbf5f,0x3eb83efc,0x3e60bf65,0x3f7abee6,0xbf09bea1,0x3f58bf73,
0xbf0ebe48,0x3f55bf7b,0xbf0ebe48,0x3f55bf7b,0xbf553f7b,0xbf0ebe48,0xbf553f7b,0xbf0ebe48,0x3f0e3e48,0xbf553f7b,0x3f0e3e48,0xbf553f7b,
0x3f55bf7b,0x3f0e3e48,0x3f55bf7b,0x3f0e3e48,0xbecfbe89,0x3f6abf77,0x3eb8bf5f,0x3f6fbefc,0xbf7a3f65,0xbe60bee6,0xbf583ea1,0x3f09bf73,
0x3cc93f1d,0xbf803f4a,0xbf313f7e,0xbf393dfb,0x3f7cbf27,0xbe2f3f42,0x3f133d97,0xbf513f7f,0xbe79beac,0x3f78bf71,0x3f78bf71,0x3e793eac,
0xbf7d3f3e,0x3e16bf2c,0x3e16bf2c,0x3f7dbf3e,0xbf043f67,0xbf5c3edb,0xbf5c3edb,0x3f04bf67,0x3f18bd49,0xbf4e3f80,0xbf4e3f80,0xbf183d49,
0xbd97becf,0x3f7fbf6a,0x3f42beb8,0xbf273f6f,0xbf5f3f09,0x3efcbf58,0x3f77bf7a,0x3e893e60,0xbf653f80,0xbee6bcc9,0x3ea1bf39,0x3f73bf31,
0xbdfb3f13,0xbf7e3f51,0xbf1d3e2f,0x3f4abf7c,0x3dc9bef1,0x3f7fbf62,0xbdc93ef1,0xbf7f3f62,0xbf223e95,0x3f46bf75,0x3f22be95,0xbf463f75,
0xbf7f3f62,0x3dc9bef1,0x3f7fbf62,0xbdc93ef1,0xbf463f75,0xbf223e95,0x3f46bf75,0x3f22be95,0x3e89bf09,0x3f77bf58,0xbf5f3f7a,0xbefc3e60,
0xbea13cc9,0x3f73bf80,0xbee63f31,0xbf653f39,0xbf4a3f13,0x3f1dbf51,0x3dfb3e2f,0xbf7e3f7c,0xbf7f3f6f,0x3d97beb8,0x3f27becf,0xbf423f6a,
0x3edbbf18,0x3f67bf4e,0xbf673f4e,0x3edbbf18,0x3d49be79,0x3f80bf78,0xbf803f78,0x3d49be79,0xbeac3e16,0x3f71bf7d,0xbf713f7d,0xbeac3e16,
0xbf2c3f04,0x3f3ebf5c,0xbf3e3f5c,0xbf2c3f04,0x3f13bf27,0x3f51bf42,0xbe2f3d97,0x3f7cbf7f,0x3ecfbefc,0x3f6abf5f,0xbeb83e89,0x3f6fbf77,
0x3e60bea1,0x3f7abf73,0xbf093ee6,0x3f58bf65,0x3cc9bdfb,0x3f80bf7e,0xbf313f1d,0x3f39bf4a,0x3f803f80,0xbf353f35,0x3f803f80,0xbf353f35,
0x3f803f80,0xbf353f35,0x3f803f80,0xbf353f35,0x3f803f80,0xbf353f35,0x3f803f80,0xbf353f35,0x3f803f80,0xbf353f35,0x3f803f80,0xbf353f35,
0xbe2fbd97,0xbf7cbf7f,0xbf51bf42,0xbf13bf27,0xbeb8be89,0xbf6fbf77,0xbf6abf5f,0xbecfbefc,0xbf09bee6,0xbf58bf65,0xbf7abf73,0xbe60bea1,
0xbf31bf1d,0xbf39bf4a,0xbf80bf7e,0xbcc9bdfb,0xbf71bf7d,0x3eac3e16,0x3eac3e16,0x3f713f7d,0xbf3ebf5c,0x3f2c3f04,0x3f2c3f04,0x3f3e3f5c,
0xbedbbf18,0x3f673f4e,0x3f673f4e,0x3edb3f18,0xbd49be79,0x3f803f78,0x3f803f78,0x3d493e79,0x3efc3e60,0x3f5f3f7a,0x3e893f09,0xbf77bf58,
0x3f653f39,0x3ee63f31,0xbea1bcc9,0xbf73bf80,0x3f7e3f7c,0xbdfb3e2f,0xbf4abf13,0xbf1dbf51,0x3f423f6a,0xbf27becf,0xbf7fbf6f,0xbd97beb8,
0x3f463f75,0xbf22be95,0xbf46bf75,0x3f223e95,0x3dc93ef1,0xbf7fbf62,0xbdc9bef1,0x3f7f3f62,0xbf22be95,0xbf46bf75,0x3f223e95,0x3f463f75,
0xbf7fbf62,0xbdc9bef1,0x3f7f3f62,0x3dc93ef1,0xbf42beb8,0xbf27bf6f,0x3f7f3f6a,0xbd973ecf,0xbf77bf7a,0x3e89be60,0x3efc3f58,0xbf5fbf09,
0xbea1bf39,0x3f733f31,0xbee63cc9,0xbf65bf80,0x3f1d3e2f,0x3f4a3f7c,0xbf7ebf51,0xbdfbbf13,0xbf04bf67,0x3f5c3edb,0xbf5cbedb,0xbf04bf67,
0x3f183d49,0x3f4e3f80,0xbf4ebf80,0x3f183d49,0x3f783f71,0xbe793eac,0x3e79beac,0x3f783f71,0x3e163f2c,0xbf7dbf3e,0x3f7d3f3e,0x3e163f2c,
0x3f6f3efc,0x3eb83f5f,0x3ecfbe89,0x3f6a3f77,0x3f093f73,0xbf58bea1,0x3f7a3f65,0xbe603ee6,0xbf39bdfb,0xbf31bf7e,0xbcc93f1d,0xbf80bf4a,
0xbf51bf7f,0x3f13bd97,0xbf7cbf27,0xbe2fbf42,0x3e483f55,0xbf7bbf0e,0x3e483f55,0xbf7bbf0e,0xbf7bbf0e,0xbe48bf55,0xbf7bbf0e,0xbe48bf55,
0xbe48bf55,0x3f7b3f0e,0xbe48bf55,0x3f7b3f0e,0x3f7b3f0e,0x3e483f55,0x3f7b3f0e,0x3e483f55,0xbf80bf1d,0xbcc9bf4a,0xbf39bf7e,0x3f31bdfb,
0x3e2fbf27,0x3f7c3f42,0x3f513d97,0x3f133f7f,0x3f6f3f5f,0xbeb83efc,0x3ecf3f77,0xbf6abe89,0xbf093ea1,0xbf58bf73,0xbf7abee6,0xbe60bf65,
0x3e16bf3e,0x3f7d3f2c,0x3f7d3f2c,0xbe163f3e,0x3f5c3f67,0xbf043edb,0xbf043edb,0xbf5cbf67,0xbf4e3d49,0xbf18bf80,0xbf18bf80,0x3f4ebd49,
0xbe79bf71,0x3f783eac,0x3f783eac,0x3e793f71,0x3f733f39,0xbea13f31,0xbf65bcc9,0xbee6bf80,0xbf4a3e2f,0xbf1dbf7c,0x3dfbbf51,0x3f7e3f13,
0xbd97bf6a,0x3f7f3ecf,0x3f423f6f,0xbf273eb8,0x3f5f3f58,0xbefc3f09,0xbf77be60,0xbe89bf7a,0xbef13f22,0xbf62bf46,0x3ef1bf22,0x3f623f46,
0xbe95bf7f,0x3f753dc9,0x3e953f7f,0xbf75bdc9,0x3f623f46,0xbef13f22,0xbf62bf46,0x3ef1bf22,0xbf75bdc9,0xbe95bf7f,0x3f753dc9,0x3e953f7f,
0xbf4abf51,0x3f1dbf13,0x3dfb3f7c,0xbf7ebe2f,0x3f7f3eb8,0xbd973f6f,0xbf27bf6a,0x3f42becf,0xbf5f3e60,0xbefcbf7a,0x3f773f09,0xbe893f58,
0x3ee6bf39,0x3f653f31,0xbf733cc9,0xbea1bf80,0x3f3ebf04,0x3f2c3f5c,0xbf2cbf5c,0x3f3ebf04,0xbedb3f4e,0xbf67bf18,0x3f673f18,0xbedb3f4e,
0x3d49bf78,0x3f803e79,0xbf80be79,0x3d49bf78,0x3eac3f7d,0xbf713e16,0x3f71be16,0x3eac3f7d,0x3f093f65,0xbf583ee6,0x3f7a3ea1,0xbe603f73,
0xbf31bf4a,0x3f39bf1d,0xbf80bdfb,0x3cc9bf7e,0x3f513f27,0xbf133f42,0x3f7cbd97,0x3e2f3f7f,0xbf6abefc,0x3ecfbf5f,0xbf6f3e89,0xbeb8bf77,
0xbf6d3ec4,0xbec4bf6d,0xbf6d3ec4,0xbec4bf6d,0x3f6dbec4,0x3ec43f6d,0x3f6dbec4,0x3ec43f6d,0xbf6d3ec4,0xbec4bf6d,0xbf6d3ec4,0xbec4bf6d,
0x3f6dbec4,0x3ec43f6d,0x3f6dbec4,0x3ec43f6d,0xbe60bf73,0x3f7abea1,0x3f09bf65,0x3f583ee6,0x3cc93f7e,0xbf803dfb,0xbf313f4a,0xbf39bf1d,
0x3e2fbf7f,0x3f7c3d97,0x3f51bf27,0x3f133f42,0xbeb83f77,0xbf6fbe89,0xbf6a3efc,0xbecfbf5f,0x3f80be79,0x3d493f78,0x3d493f78,0xbf803e79,
0xbf71be16,0x3eacbf7d,0x3eacbf7d,0x3f713e16,0x3f3e3f04,0xbf2c3f5c,0xbf2c3f5c,0xbf3ebf04,0xbedbbf4e,0x3f67bf18,0x3f67bf18,0x3edb3f4e,
0xbdfb3f7c,0xbf7e3e2f,0xbf1dbf13,0x3f4abf51,0x3f27bf6a,0x3f423ecf,0x3d973f6f,0xbf7f3eb8,0xbf773f09,0xbe89bf58,0x3efcbf7a,0x3f5f3e60,
0x3f733cc9,0xbea13f80,0xbf653f31,0xbee6bf39,0xbf753dc9,0x3e95bf7f,0x3f75bdc9,0xbe953f7f,0x3ef13f22,0xbf623f46,0xbef1bf22,0x3f62bf46,
0x3e95bf7f,0x3f75bdc9,0xbe953f7f,0xbf753dc9,0xbf623f46,0xbef1bf22,0x3f62bf46,0x3ef13f22,0x3ee6bf80,0x3f65bcc9,0xbf733f39,0xbea1bf31,
0xbf7e3f13,0xbdfbbf51,0x3f4a3e2f,0xbf1d3f7c,0x3f273eb8,0xbf423f6f,0x3d97bf6a,0x3f7fbecf,0x3e89bf7a,0x3f77be60,0xbf5f3f58,0xbefcbf09,
0x3f4e3d49,0xbf183f80,0x3f18bf80,0x3f4e3d49,0x3e79bf71,0x3f78beac,0xbf783eac,0x3e79bf71,0xbf7d3f2c,0xbe16bf3e,0x3e163f3e,0xbf7d3f2c,
0x3f043edb,0xbf5c3f67,0x3f5cbf67,0x3f043edb,0xbf393f7e,0xbf31bdfb,0xbcc93f4a,0xbf803f1d,0x3f51bd97,0xbf133f7f,0x3f7cbf42,0x3e2f3f27,
0x3ecfbf77,0x3f6abe89,0xbeb8befc,0x3f6fbf5f,0xbf7a3ee6,0x3e60bf65,0xbf583f73,0xbf09bea1,0xbf0ebe48,0x3f55bf7b,0xbf0ebe48,0x3f55bf7b,
0xbf553f7b,0xbf0ebe48,0xbf553f7b,0xbf0ebe48,0x3f0e3e48,0xbf553f7b,0x3f0e3e48,0xbf553f7b,0x3f55bf7b,0x3f0e3e48,0x3f55bf7b,0x3f0e3e48,
0x3f6abf77,0x3ecf3e89,0x3f6fbefc,0xbeb83f5f,0xbe60bee6,0x3f7abf65,0x3f09bf73,0x3f58bea1,0xbf803f4a,0xbcc9bf1d,0xbf393dfb,0x3f31bf7e,
0xbe2f3f42,0xbf7c3f27,0xbf513f7f,0xbf13bd97,0x3e793eac,0xbf783f71,0xbf783f71,0xbe79beac,0x3f7dbf3e,0xbe163f2c,0xbe163f2c,0xbf7d3f3e,
0x3f04bf67,0x3f5cbedb,0x3f5cbedb,0xbf043f67,0xbf183d49,0x3f4ebf80,0x3f4ebf80,0x3f18bd49,0xbf7f3f6a,0xbd97becf,0x3f27bf6f,0x3f42beb8,
0xbefc3f58,0xbf5f3f09,0xbe89be60,0x3f77bf7a,0x3ee63cc9,0xbf653f80,0xbf733f31,0x3ea1bf39,0x3f7ebf51,0xbdfb3f13,0xbf4a3f7c,0xbf1d3e2f,
0x3dc9bef1,0x3f7fbf62,0xbdc93ef1,0xbf7f3f62,0xbf223e95,0x3f46bf75,0x3f22be95,0xbf463f75,0xbf7f3f62,0x3dc9bef1,0x3f7fbf62,0xbdc93ef1,
0xbf463f75,0xbf223e95,0x3f46bf75,0x3f22be95,0x3f77bf58,0xbe893f09,0xbefc3e60,0x3f5fbf7a,0x3f73bf80,0x3ea1bcc9,0xbf653f39,0x3ee6bf31,
0x3f1dbf51,0x3f4abf13,0xbf7e3f7c,0xbdfbbe2f,0x3d97beb8,0x3f7fbf6f,0xbf423f6a,0xbf273ecf,0xbedb3f18,0xbf673f4e,0x3f67bf4e,0xbedb3f18,
0xbd493e79,0xbf803f78,0x3f80bf78,0xbd493e79,0x3eacbe16,0xbf713f7d,0x3f71bf7d,0x3eacbe16,0x3f2cbf04,0xbf3e3f5c,0x3f3ebf5c,0x3f2cbf04,
0xbf513f42,0x3f13bf27,0xbf7c3f7f,0xbe2f3d97,0xbf6a3f5f,0x3ecfbefc,0xbf6f3f77,0xbeb83e89,0xbf7a3f73,0x3e60bea1,0xbf583f65,0xbf093ee6,
0xbf803f7e,0x3cc9bdfb,0xbf393f4a,0xbf313f1d,0x3f803f80,0xbf353f35,0x3f803f80,0xbf353f35,0x3f803f80,0xbf353f35,0x3f803f80,0xbf353f35,
0x3f803f80,0xbf353f35,0x3f803f80,0xbf353f35,0x3f803f80,0xbf353f35,0x3f803f80,0xbf353f35,0xbf7cbf7f,0x3e2f3d97,0xbf13bf27,0x3f513f42,
0xbf6fbf77,0x3eb83e89,0xbecfbefc,0x3f6a3f5f,0xbf58bf65,0x3f093ee6,0xbe60bea1,0x3f7a3f73,0xbf39bf4a,0x3f313f1d,0xbcc9bdfb,0x3f803f7e,
0x3f713f7d,0xbeacbe16,0xbeacbe16,0xbf71bf7d,0x3f3e3f5c,0xbf2cbf04,0xbf2cbf04,0xbf3ebf5c,0x3edb3f18,0xbf67bf4e,0xbf67bf4e,0xbedbbf18,
0x3d493e79,0xbf80bf78,0xbf80bf78,0xbd49be79,0xbf5fbf7a,0x3efc3e60,0x3f773f58,0x3e893f09,0xbee6bf31,0x3f653f39,0x3f733f80,0xbea1bcc9,
0x3dfbbe2f,0x3f7e3f7c,0x3f1d3f51,0xbf4abf13,0x3f273ecf,0x3f423f6a,0x3d973eb8,0xbf7fbf6f,0x3f463f75,0xbf22be95,0xbf46bf75,0x3f223e95,
0x3dc93ef1,0xbf7fbf62,0xbdc9bef1,0x3f7f3f62,0xbf22be95,0xbf46bf75,0x3f223e95,0x3f463f75,0xbf7fbf62,0xbdc9bef1,0x3f7f3f62,0x3dc93ef1,
0xbf27bf6f,0x3f423eb8,0xbd973ecf,0xbf7fbf6a,0x3e89be60,0x3f773f7a,0xbf5fbf09,0xbefcbf58,0x3f733f31,0x3ea13f39,0xbf65bf80,0x3ee6bcc9,
0x3f4a3f7c,0xbf1dbe2f,0xbdfbbf13,0x3f7e3f51,0x3f043f67,0xbf5cbedb,0x3f5c3edb,0x3f043f67,0xbf18bd49,0xbf4ebf80,0x3f4e3f80,0xbf18bd49,
0xbf78bf71,0x3e79beac,0xbe793eac,0xbf78bf71,0xbe16bf2c,0x3f7d3f3e,0xbf7dbf3e,0xbe16bf2c,0xbeb8bf5f,0x3f6f3efc,0xbf6abf77,0x3ecfbe89,
0x3f583ea1,0x3f093f73,0x3e60bee6,0x3f7a3f65,0x3f313f7e,0xbf39bdfb,0x3f803f4a,0xbcc93f1d,0xbf133d97,0xbf51bf7f,0x3e2f3f42,0xbf7cbf27,
0x3e483f55,0xbf7bbf0e,0x3e483f55,0xbf7bbf0e,0xbf7bbf0e,0xbe48bf55,0xbf7bbf0e,0xbe48bf55,0xbe48bf55,0x3f7b3f0e,0xbe48bf55,0x3f7b3f0e,
0x3f7b3f0e,0x3e483f55,0x3f7b3f0e,0x3e483f55,0xbcc9bf4a,0x3f803f1d,0x3f31bdfb,0x3f393f7e,0x3f7c3f42,0xbe2f3f27,0x3f133f7f,0xbf51bd97,
0xbeb83efc,0xbf6fbf5f,0xbf6abe89,0xbecfbf77,0xbf58bf73,0x3f09bea1,0xbe60bf65,0x3f7a3ee6,0xbe163f3e,0xbf7dbf2c,0xbf7dbf2c,0x3e16bf3e,
0xbf5cbf67,0x3f04bedb,0x3f04bedb,0x3f5c3f67,0x3f4ebd49,0x3f183f80,0x3f183f80,0xbf4e3d49,0x3e793f71,0xbf78beac,0xbf78beac,0xbe79bf71,
0x3ea1bf31,0x3f733f39,0x3ee63f80,0xbf65bcc9,0x3f1d3f7c,0xbf4a3e2f,0xbf7ebf13,0x3dfbbf51,0xbf7fbecf,0xbd97bf6a,0x3f27beb8,0x3f423f6f,
0x3efcbf09,0x3f5f3f58,0x3e893f7a,0xbf77be60,0xbef13f22,0xbf62bf46,0x3ef1bf22,0x3f623f46,0xbe95bf7f,0x3f753dc9,0x3e953f7f,0xbf75bdc9,
0x3f623f46,0xbef13f22,0xbf62bf46,0x3ef1bf22,0xbf75bdc9,0xbe95bf7f,0x3f753dc9,0x3e953f7f,0x3f1dbf13,0x3f4a3f51,0xbf7ebe2f,0xbdfbbf7c,
0xbd973f6f,0xbf7fbeb8,0x3f42becf,0x3f273f6a,0xbefcbf7a,0x3f5fbe60,0xbe893f58,0xbf77bf09,0x3f653f31,0xbee63f39,0xbea1bf80,0x3f73bcc9,
0xbf3e3f04,0xbf2cbf5c,0x3f2c3f5c,0xbf3e3f04,0x3edbbf4e,0x3f673f18,0xbf67bf18,0x3edbbf4e,0xbd493f78,0xbf80be79,0x3f803e79,0xbd493f78,
0xbeacbf7d,0x3f71be16,0xbf713e16,0xbeacbf7d,0x3f58bee6,0x3f093f65,0x3e60bf73,0x3f7a3ea1,0xbf393f1d,0xbf31bf4a,0xbcc93f7e,0xbf80bdfb,
0x3f13bf42,0x3f513f27,0xbe2fbf7f,0x3f7cbd97,0xbecf3f5f,0xbf6abefc,0x3eb83f77,0xbf6f3e89,0xbf6d3ec4,0xbec4bf6d,0xbf6d3ec4,0xbec4bf6d,
0x3f6dbec4,0x3ec43f6d,0x3f6dbec4,0x3ec43f6d,0xbf6d3ec4,0xbec4bf6d,0xbf6d3ec4,0xbec4bf6d,0x3f6dbec4,0x3ec43f6d,0x3f6dbec4,0x3ec43f6d,
0x3f7abea1,0x3e603f73,0x3f583ee6,0xbf093f65,0xbf803dfb,0xbcc9bf7e,0xbf39bf1d,0x3f31bf4a,0x3f7c3d97,0xbe2f3f7f,0x3f133f42,0xbf513f27,
0xbf6fbe89,0x3eb8bf77,0xbecfbf5f,0x3f6abefc,0xbf803e79,0xbd49bf78,0xbd49bf78,0x3f80be79,0x3f713e16,0xbeac3f7d,0xbeac3f7d,0xbf71be16,
0xbf3ebf04,0x3f2cbf5c,0x3f2cbf5c,0x3f3e3f04,0x3edb3f4e,0xbf673f18,0xbf673f18,0xbedbbf4e,0x3f7ebe2f,0xbdfb3f7c,0xbf4a3f51,0xbf1dbf13,
0xbf42becf,0x3f27bf6a,0x3f7fbeb8,0x3d973f6f,0x3e893f58,0xbf773f09,0xbf5fbe60,0x3efcbf7a,0x3ea1bf80,0x3f733cc9,0x3ee63f39,0xbf653f31,
0xbf753dc9,0x3e95bf7f,0x3f75bdc9,0xbe953f7f,0x3ef13f22,0xbf623f46,0xbef1bf22,0x3f62bf46,0x3e95bf7f,0x3f75bdc9,0xbe953f7f,0xbf753dc9,
0xbf623f46,0xbef1bf22,0x3f62bf46,0x3ef13f22,0x3f65bcc9,0xbee63f80,0xbea1bf31,0x3f73bf39,0xbdfbbf51,0x3f7ebf13,0xbf1d3f7c,0xbf4abe2f,
0xbf423f6f,0xbf27beb8,0x3f7fbecf,0xbd973f6a,0x3f77be60,0xbe893f7a,0xbefcbf09,0x3f5fbf58,0xbf4ebd49,0x3f18bf80,0xbf183f80,0xbf4ebd49,
0xbe793f71,0xbf783eac,0x3f78beac,0xbe793f71,0x3f7dbf2c,0x3e163f3e,0xbe16bf3e,0x3f7dbf2c,0xbf04bedb,0x3f5cbf67,0xbf5c3f67,0xbf04bedb,
0x3f313dfb,0xbf393f7e,0x3f80bf1d,0xbcc93f4a,0x3f13bf7f,0x3f51bd97,0xbe2fbf27,0x3f7cbf42,0xbf6a3e89,0x3ecfbf77,0xbf6f3f5f,0xbeb8befc,
0xbe603f65,0xbf7a3ee6,0x3f093ea1,0xbf583f73,0xbf0ebe48,0x3f55bf7b,0xbf0ebe48,0x3f55bf7b,0xbf553f7b,0xbf0ebe48,0xbf553f7b,0xbf0ebe48,
0x3f0e3e48,0xbf553f7b,0x3f0e3e48,0xbf553f7b,0x3f55bf7b,0x3f0e3e48,0x3f55bf7b,0x3f0e3e48,0x3ecf3e89,0xbf6a3f77,0xbeb83f5f,0xbf6f3efc,
0x3f7abf65,0x3e603ee6,0x3f58bea1,0xbf093f73,0xbcc9bf1d,0x3f80bf4a,0x3f31bf7e,0x3f39bdfb,0xbf7c3f27,0x3e2fbf42,0xbf13bd97,0x3f51bf7f,
0xbe79beac,0x3f78bf71,0x3f78bf71,0x3e793eac,0xbf7d3f3e,0x3e16bf2c,0x3e16bf2c,0x3f7dbf3e,0xbf043f67,0xbf5c3edb,0xbf5c3edb,0x3f04bf67,
0x3f18bd49,0xbf4e3f80,0xbf4e3f80,0xbf183d49,0x3d973ecf,0xbf7f3f6a,0xbf423eb8,0x3f27bf6f,0x3f5fbf09,0xbefc3f58,0xbf773f7a,0xbe89be60,
0x3f65bf80,0x3ee63cc9,0xbea13f39,0xbf733f31,0x3dfbbf13,0x3f7ebf51,0x3f1dbe2f,0xbf4a3f7c,0x3dc9bef1,0x3f7fbf62,0xbdc93ef1,0xbf7f3f62,
0xbf223e95,0x3f46bf75,0x3f22be95,0xbf463f75,0xbf7f3f62,0x3dc9bef1,0x3f7fbf62,0xbdc93ef1,0xbf463f75,0xbf223e95,0x3f46bf75,0x3f22be95,
0xbe893f09,0xbf773f58,0x3f5fbf7a,0x3efcbe60,0x3ea1bcc9,0xbf733f80,0x3ee6bf31,0x3f65bf39,0x3f4abf13,0xbf1d3f51,0xbdfbbe2f,0x3f7ebf7c,
0x3f7fbf6f,0xbd973eb8,0xbf273ecf,0x3f42bf6a,0x3edbbf18,0x3f67bf4e,0xbf673f4e,0x3edbbf18,0x3d49be79,0x3f80bf78,0xbf803f78,0x3d49be79,
0xbeac3e16,0x3f71bf7d,0xbf713f7d,0xbeac3e16,0xbf2c3f04,0x3f3ebf5c,0xbf3e3f5c,0xbf2c3f04,0xbf133f27,0xbf513f42,0x3e2fbd97,0xbf7c3f7f,
0xbecf3efc,0xbf6a3f5f,0x3eb8be89,0xbf6f3f77,0xbe603ea1,0xbf7a3f73,0x3f09bee6,0xbf583f65,0xbcc93dfb,0xbf803f7e,0x3f31bf1d,0xbf393f4a,
0x3f803f80,0xbf353f35,0x3f803f80,0xbf353f35,0x3f803f80,0xbf353f35,0x3f803f80,0xbf353f35,0x3f803f80,0xbf353f35,0x3f803f80,0xbf353f35,
0x3f803f80,0xbf353f35,0x3f803f80,0xbf353f35,0x3e2f3d97,0x3f7c3f7f,0x3f513f42,0x3f133f27,0x3eb83e89,0x3f6f3f77,0x3f6a3f5f,0x3ecf3efc,
0x3f093ee6,0x3f583f65,0x3f7a3f73,0x3e603ea1,0x3f313f1d,0x3f393f4a,0x3f803f7e,0x3cc93dfb,0xbf71bf7d,0x3eac3e16,0x3eac3e16,0x3f713f7d,
0xbf3ebf5c,0x3f2c3f04,0x3f2c3f04,0x3f3e3f5c,0xbedbbf18,0x3f673f4e,0x3f673f4e,0x3edb3f18,0xbd49be79,0x3f803f78,0x3f803f78,0x3d493e79,
0xbefcbe60,0xbf5fbf7a,0xbe89bf09,0x3f773f58,0xbf65bf39,0xbee6bf31,0x3ea13cc9,0x3f733f80,0xbf7ebf7c,0x3dfbbe2f,0x3f4a3f13,0x3f1d3f51,
0xbf42bf6a,0x3f273ecf,0x3f7f3f6f,0x3d973eb8,0x3f463f75,0xbf22be95,0xbf46bf75,0x3f223e95,0x3dc93ef1,0xbf7fbf62,0xbdc9bef1,0x3f7f3f62,
0xbf22be95,0xbf46bf75,0x3f223e95,0x3f463f75,0xbf7fbf62,0xbdc9bef1,0x3f7f3f62,0x3dc93ef1,0x3f423eb8,0x3f273f6f,0xbf7fbf6a,0x3d97becf,
0x3f773f7a,0xbe893e60,0xbefcbf58,0x3f5f3f09,0x3ea13f39,0xbf73bf31,0x3ee6bcc9,0x3f653f80,0xbf1dbe2f,0xbf4abf7c,0x3f7e3f51,0x3dfb3f13,
0xbf04bf67,0x3f5c3edb,0xbf5cbedb,0xbf04bf67,0x3f183d49,0x3f4e3f80,0xbf4ebf80,0x3f183d49,0x3f783f71,0xbe793eac,0x3e79beac,0x3f783f71,
0x3e163f2c,0xbf7dbf3e,0x3f7d3f3e,0x3e163f2c,0xbf6fbefc,0xbeb8bf5f,0xbecf3e89,0xbf6abf77,0xbf09bf73,0x3f583ea1,0xbf7abf65,0x3e60bee6,
0x3f393dfb,0x3f313f7e,0x3cc9bf1d,0x3f803f4a,0x3f513f7f,0xbf133d97,0x3f7c3f27,0x3e2f3f42,0x3e483f55,0xbf7bbf0e,0x3e483f55,0xbf7bbf0e,
0xbf7bbf0e,0xbe48bf55,0xbf7bbf0e,0xbe48bf55,0xbe48bf55,0x3f7b3f0e,0xbe48bf55,0x3f7b3f0e,0x3f7b3f0e,0x3e483f55,0x3f7b3f0e,0x3e483f55,
0x3f803f1d,0x3cc93f4a,0x3f393f7e,0xbf313dfb,0xbe2f3f27,0xbf7cbf42,0xbf51bd97,0xbf13bf7f,0xbf6fbf5f,0x3eb8befc,0xbecfbf77,0x3f6a3e89,
0x3f09bea1,0x3f583f73,0x3f7a3ee6,0x3e603f65,0x3e16bf3e,0x3f7d3f2c,0x3f7d3f2c,0xbe163f3e,0x3f5c3f67,0xbf043edb,0xbf043edb,0xbf5cbf67,
0xbf4e3d49,0xbf18bf80,0xbf18bf80,0x3f4ebd49,0xbe79bf71,0x3f783eac,0x3f783eac,0x3e793f71,0xbf73bf39,0x3ea1bf31,0x3f653cc9,0x3ee63f80,
0x3f4abe2f,0x3f1d3f7c,0xbdfb3f51,0xbf7ebf13,0x3d973f6a,0xbf7fbecf,0xbf42bf6f,0x3f27beb8,0xbf5fbf58,0x3efcbf09,0x3f773e60,0x3e893f7a,
0xbef13f22,0xbf62bf46,0x3ef1bf22,0x3f623f46,0xbe95bf7f,0x3f753dc9,0x3e953f7f,0xbf75bdc9,0x3f623f46,0xbef13f22,0xbf62bf46,0x3ef1bf22,
0xbf75bdc9,0xbe95bf7f,0x3f753dc9,0x3e953f7f,0x3f4a3f51,0xbf1d3f13,0xbdfbbf7c,0x3f7e3e2f,0xbf7fbeb8,0x3d97bf6f,0x3f273f6a,0xbf423ecf,
0x3f5fbe60,0x3efc3f7a,0xbf77bf09,0x3e89bf58,0xbee63f39,0xbf65bf31,0x3f73bcc9,0x3ea13f80,0x3f3ebf04,0x3f2c3f5c,0xbf2cbf5c,0x3f3ebf04,
0xbedb3f4e,0xbf67bf18,0x3f673f18,0xbedb3f4e,0x3d49bf78,0x3f803e79,0xbf80be79,0x3d49bf78,0x3eac3f7d,0xbf713e16,0x3f71be16,0x3eac3f7d,
0xbf09bf65,0x3f58bee6,0xbf7abea1,0x3e60bf73,0x3f313f4a,0xbf393f1d,0x3f803dfb,0xbcc93f7e,0xbf51bf27,0x3f13bf42,0xbf7c3d97,0xbe2fbf7f,
0x3f6a3efc,0xbecf3f5f,0x3f6fbe89,0x3eb83f77,0xbf6d3ec4,0xbec4bf6d,0xbf6d3ec4,0xbec4bf6d,0x3f6dbec4,0x3ec43f6d,0x3f6dbec4,0x3ec43f6d,
0xbf6d3ec4,0xbec4bf6d,0xbf6d3ec4,0xbec4bf6d,0x3f6dbec4,0x3ec43f6d,0x3f6dbec4,0x3ec43f6d,0x3e603f73,0xbf7a3ea1,0xbf093f65,0xbf58bee6,
0xbcc9bf7e,0x3f80bdfb,0x3f31bf4a,0x3f393f1d,0xbe2f3f7f,0xbf7cbd97,0xbf513f27,0xbf13bf42,0x3eb8bf77,0x3f6f3e89,0x3f6abefc,0x3ecf3f5f,
0x3f80be79,0x3d493f78,0x3d493f78,0xbf803e79,0xbf71be16,0x3eacbf7d,0x3eacbf7d,0x3f713e16,0x3f3e3f04,0xbf2c3f5c,0xbf2c3f5c,0xbf3ebf04,
0xbedbbf4e,0x3f67bf18,0x3f67bf18,0x3edb3f4e,0x3dfbbf7c,0x3f7ebe2f,0x3f1d3f13,0xbf4a3f51,0xbf273f6a,0xbf42becf,0xbd97bf6f,0x3f7fbeb8,
0x3f77bf09,0x3e893f58,0xbefc3f7a,0xbf5fbe60,0xbf73bcc9,0x3ea1bf80,0x3f65bf31,0x3ee63f39,0xbf753dc9,0x3e95bf7f,0x3f75bdc9,0xbe953f7f,
0x3ef13f22,0xbf623f46,0xbef1bf22,0x3f62bf46,0x3e95bf7f,0x3f75bdc9,0xbe953f7f,0xbf753dc9,0xbf623f46,0xbef1bf22,0x3f62bf46,0x3ef13f22,
0xbee63f80,0xbf653cc9,0x3f73bf39,0x3ea13f31,0x3f7ebf13,0x3dfb3f51,0xbf4abe2f,0x3f1dbf7c,0xbf27beb8,0x3f42bf6f,0xbd973f6a,0xbf7f3ecf,
0xbe893f7a,0xbf773e60,0x3f5fbf58,0x3efc3f09,0x3f4e3d49,0xbf183f80,0x3f18bf80,0x3f4e3d49,0x3e79bf71,0x3f78beac,0xbf783eac,0x3e79bf71,
0xbf7d3f2c,0xbe16bf3e,0x3e163f3e,0xbf7d3f2c,0x3f043edb,0xbf5c3f67,0x3f5cbf67,0x3f043edb,0x3f39bf7e,0x3f313dfb,0x3cc9bf4a,0x3f80bf1d,
0xbf513d97,0x3f13bf7f,0xbf7c3f42,0xbe2fbf27,0xbecf3f77,0xbf6a3e89,0x3eb83efc,0xbf6f3f5f,0x3f7abee6,0xbe603f65,0x3f58bf73,0x3f093ea1,
0xbf0ebe48,0x3f55bf7b,0xbf0ebe48,0x3f55bf7b,0xbf553f7b,0xbf0ebe48,0xbf553f7b,0xbf0ebe48,0x3f0e3e48,0xbf553f7b,0x3f0e3e48,0xbf553f7b,
0x3f55bf7b,0x3f0e3e48,0x3f55bf7b,0x3f0e3e48,0xbf6a3f77,0xbecfbe89,0xbf6f3efc,0x3eb8bf5f,0x3e603ee6,0xbf7a3f65,0xbf093f73,0xbf583ea1,
0x3f80bf4a,0x3cc93f1d,0x3f39bdfb,0xbf313f7e,0x3e2fbf42,0x3f7cbf27,0x3f51bf7f,0x3f133d97,0x3e793eac,0xbf783f71,0xbf783f71,0xbe79beac,
0x3f7dbf3e,0xbe163f2c,0xbe163f2c,0xbf7d3f3e,0x3f04bf67,0x3f5cbedb,0x3f5cbedb,0xbf043f67,0xbf183d49,0x3f4ebf80,0x3f4ebf80,0x3f18bd49,
0x3f7fbf6a,0x3d973ecf,0xbf273f6f,0xbf423eb8,0x3efcbf58,0x3f5fbf09,0x3e893e60,0xbf773f7a,0xbee6bcc9,0x3f65bf80,0x3f73bf31,0xbea13f39,
0xbf7e3f51,0x3dfbbf13,0x3f4abf7c,0x3f1dbe2f,0x3dc9bef1,0x3f7fbf62,0xbdc93ef1,0xbf7f3f62,0xbf223e95,0x3f46bf75,0x3f22be95,0xbf463f75,
0xbf7f3f62,0x3dc9bef1,0x3f7fbf62,0xbdc93ef1,0xbf463f75,0xbf223e95,0x3f46bf75,0x3f22be95,0xbf773f58,0x3e89bf09,0x3efcbe60,0xbf5f3f7a,
0xbf733f80,0xbea13cc9,0x3f65bf39,0xbee63f31,0xbf1d3f51,0xbf4a3f13,0x3f7ebf7c,0x3dfb3e2f,0xbd973eb8,0xbf7f3f6f,0x3f42bf6a,0x3f27becf,
0xbedb3f18,0xbf673f4e,0x3f67bf4e,0xbedb3f18,0xbd493e79,0xbf803f78,0x3f80bf78,0xbd493e79,0x3eacbe16,0xbf713f7d,0x3f71bf7d,0x3eacbe16,
0x3f2cbf04,0xbf3e3f5c,0x3f3ebf5c,0x3f2cbf04,0x3f51bf42,0xbf133f27,0x3f7cbf7f,0x3e2fbd97,0x3f6abf5f,0xbecf3efc,0x3f6fbf77,0x3eb8be89,
0x3f7abf73,0xbe603ea1,0x3f58bf65,0x3f09bee6,0x3f80bf7e,0xbcc93dfb,0x3f39bf4a,0x3f31bf1d,0x3f803f80,0x3f803f80,0x3f803f80,0x3f803f80,
0x0,0x0,0x0,0x0,0x3f803f80,0x3f803f80,0x3f803f80,0x3f803f80,0x0,0x0,0x0,0x0,
0x3f803f80,0x3f803f80,0x3f803f80,0x3f803f80,0x0,0x0,0x0,0x0,0x3f803f80,0x3f803f80,0x3f803f80,0x3f803f80,
0x0,0x0,0x0,0x0,0x3e480000,0x3f0e3ec4,0x3f553f35,0x3f7b3f6d,0x3f7b3f80,0x3f553f6d,0x3f0e3f35,0x3e483ec4,
0x3f7b3f80,0x3f553f6d,0x3f0e3f35,0x3e483ec4,0xbe480000,0xbf0ebec4,0xbf55bf35,0xbf7bbf6d,0xbe480000,0xbf0ebec4,0xbf55bf35,0xbf7bbf6d,
0xbf7bbf80,0xbf55bf6d,0xbf0ebf35,0xbe48bec4,0xbf7bbf80,0xbf55bf6d,0xbf0ebf35,0xbe48bec4,0x3e480000,0x3f0e3ec4,0x3f553f35,0x3f7b3f6d,
0xbf6dbf80,0xbec4bf35,0x3ec40000,0x3f6d3f35,0xbec40000,0xbf6dbf35,0xbf6dbf80,0xbec4bf35,0x3f6d3f80,0x3ec43f35,0xbec40000,0xbf6dbf35,
0x3ec40000,0x3f6d3f35,0x3f6d3f80,0x3ec43f35,0xbf6dbf80,0xbec4bf35,0x3ec40000,0x3f6d3f35,0xbec40000,0xbf6dbf35,0xbf6dbf80,0xbec4bf35,
0x3f6d3f80,0x3ec43f35,0xbec40000,0xbf6dbf35,0x3ec40000,0x3f6d3f35,0x3f6d3f80,0x3ec43f35,0xbf55bf80,0x3e48bec4,0x3f7b3f35,0x3f0e3f6d,
0x3f0e0000,0x3f7b3f6d,0x3e483f35,0xbf55bec4,0x3f0e0000,0x3f7b3f6d,0x3e483f35,0xbf55bec4,0x3f553f80,0xbe483ec4,0xbf7bbf35,0xbf0ebf6d,
0x3f553f80,0xbe483ec4,0xbf7bbf35,0xbf0ebf6d,0xbf0e0000,0xbf7bbf6d,0xbe48bf35,0x3f553ec4,0xbf0e0000,0xbf7bbf6d,0xbe48bf35,0x3f553ec4,
0xbf55bf80,0x3e48bec4,0x3f7b3f35,0x3f0e3f6d,0x3f353f80,0xbf350000,0xbf35bf80,0x3f350000,0x3f350000,0x3f353f80,0xbf350000,0xbf35bf80,
0x3f353f80,0xbf350000,0xbf35bf80,0x3f350000,0x3f350000,0x3f353f80,0xbf350000,0xbf35bf80,0x3f353f80,0xbf350000,0xbf35bf80,0x3f350000,
0x3f350000,0x3f353f80,0xbf350000,0xbf35bf80,0x3f353f80,0xbf350000,0xbf35bf80,0x3f350000,0x3f350000,0x3f353f80,0xbf350000,0xbf35bf80,
0xbf550000,0xbe48bf6d,0x3f7b3f35,0xbf0e3ec4,0xbf0ebf80,0x3f7b3ec4,0xbe483f35,0xbf55bf6d,0xbf0ebf80,0x3f7b3ec4,0xbe483f35,0xbf55bf6d,
0x3f550000,0x3e483f6d,0xbf7bbf35,0x3f0ebec4,0x3f550000,0x3e483f6d,0xbf7bbf35,0x3f0ebec4,0x3f0e3f80,0xbf7bbec4,0x3e48bf35,0x3f553f6d,
0x3f0e3f80,0xbf7bbec4,0x3e48bf35,0x3f553f6d,0xbf550000,0xbe48bf6d,0x3f7b3f35,0xbf0e3ec4,0xbec4bf80,0x3f6d3f35,0xbf6d0000,0x3ec4bf35,
0xbf6d0000,0x3ec4bf35,0x3ec43f80,0xbf6dbf35,0x3ec43f80,0xbf6dbf35,0x3f6d0000,0xbec43f35,0x3f6d0000,0xbec43f35,0xbec4bf80,0x3f6d3f35,
0xbec4bf80,0x3f6d3f35,0xbf6d0000,0x3ec4bf35,0xbf6d0000,0x3ec4bf35,0x3ec43f80,0xbf6dbf35,0x3ec43f80,0xbf6dbf35,0x3f6d0000,0xbec43f35,
0x3f6d0000,0xbec43f35,0xbec4bf80,0x3f6d3f35,0x3e483f80,0xbf0ebf6d,0x3f553f35,0xbf7bbec4,0xbf7b0000,0x3f55bec4,0xbf0e3f35,0x3e48bf6d,
0xbf7b0000,0x3f55bec4,0xbf0e3f35,0x3e48bf6d,0xbe48bf80,0x3f0e3f6d,0xbf55bf35,0x3f7b3ec4,0xbe48bf80,0x3f0e3f6d,0xbf55bf35,0x3f7b3ec4,
0x3f7b0000,0xbf553ec4,0x3f0ebf35,0xbe483f6d,0x3f7b0000,0xbf553ec4,0x3f0ebf35,0xbe483f6d,0x3e483f80,0xbf0ebf6d,0x3f553f35,0xbf7bbec4,
0x80008000,0x80008000,0x80008000,0x80008000,0x3f803f80,0x3f803f80,0x3f803f80,0x3f803f80,0x80008000,0x80008000,0x80008000,0x80008000,
0x3f803f80,0x3f803f80,0x3f803f80,0x3f803f80,0x80008000,0x80008000,0x80008000,0x80008000,0x3f803f80,0x3f803f80,0x3f803f80,0x3f803f80,
0x80008000,0x80008000,0x80008000,0x80008000,0x3f803f80,0x3f803f80,0x3f803f80,0x3f803f80,0x3f7b3f80,0x3f553f6d,0x3f0e3f35,0x3e483ec4,
0xbe488000,0xbf0ebec4,0xbf55bf35,0xbf7bbf6d,0xbe480000,0xbf0ebec4,0xbf55bf35,0xbf7bbf6d,0xbf7bbf80,0xbf55bf6d,0xbf0ebf35,0xbe48bec4,
0xbf7bbf80,0xbf55bf6d,0xbf0ebf35,0xbe48bec4,0x3e488000,0x3f0e3ec4,0x3f553f35,0x3f7b3f6d,0x3e480000,0x3f0e3ec4,0x3f553f35,0x3f7b3f6d,
0x3f7b3f80,0x3f553f6d,0x3f0e3f35,0x3e483ec4,0x3ec48000,0x3f6d3f35,0x3f6d3f80,0x3ec43f35,0xbf6dbf80,0xbec4bf35,0x3ec40000,0x3f6d3f35,
0xbec48000,0xbf6dbf35,0xbf6dbf80,0xbec4bf35,0x3f6d3f80,0x3ec43f35,0xbec40000,0xbf6dbf35,0x3ec48000,0x3f6d3f35,0x3f6d3f80,0x3ec43f35,
0xbf6dbf80,0xbec4bf35,0x3ec40000,0x3f6d3f35,0xbec48000,0xbf6dbf35,0xbf6dbf80,0xbec4bf35,0x3f6d3f80,0x3ec43f35,0xbec40000,0xbf6dbf35,
0x3f0e0000,0x3f7b3f6d,0x3e483f35,0xbf55bec4,0x3f553f80,0xbe483ec4,0xbf7bbf35,0xbf0ebf6d,0x3f553f80,0xbe483ec4,0xbf7bbf35,0xbf0ebf6d,
0xbf0e8000,0xbf7bbf6d,0xbe48bf35,0x3f553ec4,0xbf0e0000,0xbf7bbf6d,0xbe48bf35,0x3f553ec4,0xbf55bf80,0x3e48bec4,0x3f7b3f35,0x3f0e3f6d,
0xbf55bf80,0x3e48bec4,0x3f7b3f35,0x3f0e3f6d,0x3f0e8000,0x3f7b3f6d,0x3e483f35,0xbf55bec4,0xbf358000,0xbf35bf80,0x3f358000,0x3f353f80,
0x3f353f80,0xbf350000,0xbf35bf80,0x3f350000,0xbf358000,0xbf35bf80,0x3f358000,0x3f353f80,0x3f353f80,0xbf350000,0xbf35bf80,0x3f350000,
0xbf358000,0xbf35bf80,0x3f358000,0x3f353f80,0x3f353f80,0xbf350000,0xbf35bf80,0x3f350000,0xbf358000,0xbf35bf80,0x3f358000,0x3f353f80,
0x3f353f80,0xbf350000,0xbf35bf80,0x3f350000,0xbf0ebf80,0x3f7b3ec4,0xbe483f35,0xbf55bf6d,0x3f558000,0x3e483f6d,0xbf7bbf35,0x3f0ebec4,
0x3f550000,0x3e483f6d,0xbf7bbf35,0x3f0ebec4,0x3f0e3f80,0xbf7bbec4,0x3e48bf35,0x3f553f6d,0x3f0e3f80,0xbf7bbec4,0x3e48bf35,0x3f553f6d,
0xbf558000,0xbe48bf6d,0x3f7b3f35,0xbf0e3ec4,0xbf550000,0xbe48bf6d,0x3f7b3f35,0xbf0e3ec4,0xbf0ebf80,0x3f7b3ec4,0xbe483f35,0xbf55bf6d,
0x3f6d8000,0xbec43f35,0xbec4bf80,0x3f6d3f35,0xbec4bf80,0x3f6d3f35,0xbf6d0000,0x3ec4bf35,0xbf6d8000,0x3ec4bf35,0x3ec43f80,0xbf6dbf35,
0x3ec43f80,0xbf6dbf35,0x3f6d0000,0xbec43f35,0x3f6d8000,0xbec43f35,0xbec4bf80,0x3f6d3f35,0xbec4bf80,0x3f6d3f35,0xbf6d0000,0x3ec4bf35,
0xbf6d8000,0x3ec4bf35,0x3ec43f80,0xbf6dbf35,0x3ec43f80,0xbf6dbf35,0x3f6d0000,0xbec43f35,0xbf7b0000,0x3f55bec4,0xbf0e3f35,0x3e48bf6d,
0xbe48bf80,0x3f0e3f6d,0xbf55bf35,0x3f7b3ec4,0xbe48bf80,0x3f0e3f6d,0xbf55bf35,0x3f7b3ec4,0x3f7b8000,0xbf553ec4,0x3f0ebf35,0xbe483f6d,
0x3f7b0000,0xbf553ec4,0x3f0ebf35,0xbe483f6d,0x3e483f80,0xbf0ebf6d,0x3f553f35,0xbf7bbec4,0x3e483f80,0xbf0ebf6d,0x3f553f35,0xbf7bbec4,
0xbf7b8000,0x3f55bec4,0xbf0e3f35,0x3e48bf6d,0x3f80,0xbf80,0x3f80,0xbf80,0x3f800000,0xbf800000,0x3f800000,0xbf800000,
0x3f80,0xbf80,0x3f80,0xbf80,0x3f800000,0xbf800000,0x3f800000,0xbf800000,0x3f80,0xbf80,0x3f80,0xbf80,
0x3f800000,0xbf800000,0x3f800000,0xbf800000,0x3f80,0xbf80,0x3f80,0xbf80,0x3f800000,0xbf800000,0x3f800000,0xbf800000,
0x3f7b0000,0xbf55bec4,0x3f0e3f35,0xbe48bf6d,0xbe483f80,0x3f0ebf6d,0xbf553f35,0x3f7bbec4,0xbe483f80,0x3f0ebf6d,0xbf553f35,0x3f7bbec4,
0xbf7b0000,0x3f553ec4,0xbf0ebf35,0x3e483f6d,0xbf7b0000,0x3f553ec4,0xbf0ebf35,0x3e483f6d,0x3e48bf80,0xbf0e3f6d,0x3f55bf35,0xbf7b3ec4,
0x3e48bf80,0xbf0e3f6d,0x3f55bf35,0xbf7b3ec4,0x3f7b0000,0xbf55bec4,0x3f0e3f35,0xbe48bf6d,0x3ec4bf80,0xbf6d3f35,0x3f6d0000,0xbec4bf35,
0xbf6d0000,0x3ec43f35,0x3ec4bf80,0xbf6d3f35,0xbec43f80,0x3f6dbf35,0xbf6d0000,0x3ec43f35,0x3f6d0000,0xbec4bf35,0xbec43f80,0x3f6dbf35,
0x3ec4bf80,0xbf6d3f35,0x3f6d0000,0xbec4bf35,0xbf6d0000,0x3ec43f35,0x3ec4bf80,0xbf6d3f35,0xbec43f80,0x3f6dbf35,0xbf6d0000,0x3ec43f35,
0x3f6d0000,0xbec4bf35,0xbec43f80,0x3f6dbf35,0x3f0ebf80,0xbf7b3ec4,0x3e483f35,0x3f55bf6d,0x3f550000,0x3e48bf6d,0xbf7b3f35,0x3f0e3ec4,
0x3f550000,0x3e48bf6d,0xbf7b3f35,0x3f0e3ec4,0xbf0e3f80,0x3f7bbec4,0xbe48bf35,0xbf553f6d,0xbf0e3f80,0x3f7bbec4,0xbe48bf35,0xbf553f6d,
0xbf550000,0xbe483f6d,0x3f7bbf35,0xbf0ebec4,0xbf550000,0xbe483f6d,0x3f7bbf35,0xbf0ebec4,0x3f0ebf80,0xbf7b3ec4,0x3e483f35,0x3f55bf6d,
0xbf353f80,0x3f350000,0x3f35bf80,0xbf350000,0x3f350000,0x3f35bf80,0xbf350000,0xbf353f80,0xbf353f80,0x3f350000,0x3f35bf80,0xbf350000,
0x3f350000,0x3f35bf80,0xbf350000,0xbf353f80,0xbf353f80,0x3f350000,0x3f35bf80,0xbf350000,0x3f350000,0x3f35bf80,0xbf350000,0xbf353f80,
0xbf353f80,0x3f350000,0x3f35bf80,0xbf350000,0x3f350000,0x3f35bf80,0xbf350000,0xbf353f80,0xbf0e0000,0xbf7b3f6d,0xbe483f35,0x3f55bec4,
0x3f55bf80,0xbe48bec4,0xbf7b3f35,0xbf0e3f6d,0x3f55bf80,0xbe48bec4,0xbf7b3f35,0xbf0e3f6d,0x3f0e0000,0x3f7bbf6d,0x3e48bf35,0xbf553ec4,
0x3f0e0000,0x3f7bbf6d,0x3e48bf35,0xbf553ec4,0xbf553f80,0x3e483ec4,0x3f7bbf35,0x3f0ebf6d,0xbf553f80,0x3e483ec4,0x3f7bbf35,0x3f0ebf6d,
0xbf0e0000,0xbf7b3f6d,0xbe483f35,0x3f55bec4,0x3f6dbf80,0x3ec4bf35,0xbec40000,0xbf6d3f35,0xbec40000,0xbf6d3f35,0xbf6d3f80,0xbec43f35,
0xbf6d3f80,0xbec43f35,0x3ec40000,0x3f6dbf35,0x3ec40000,0x3f6dbf35,0x3f6dbf80,0x3ec4bf35,0x3f6dbf80,0x3ec4bf35,0xbec40000,0xbf6d3f35,
0xbec40000,0xbf6d3f35,0xbf6d3f80,0xbec43f35,0xbf6d3f80,0xbec43f35,0x3ec40000,0x3f6dbf35,0x3ec40000,0x3f6dbf35,0x3f6dbf80,0x3ec4bf35,
0xbf7b3f80,0xbf553f6d,0xbf0e3f35,0xbe483ec4,0xbe480000,0xbf0e3ec4,0xbf553f35,0xbf7b3f6d,0xbe480000,0xbf0e3ec4,0xbf553f35,0xbf7b3f6d,
0x3f7bbf80,0x3f55bf6d,0x3f0ebf35,0x3e48bec4,0x3f7bbf80,0x3f55bf6d,0x3f0ebf35,0x3e48bec4,0x3e480000,0x3f0ebec4,0x3f55bf35,0x3f7bbf6d,
0x3e480000,0x3f0ebec4,0x3f55bf35,0x3f7bbf6d,0xbf7b3f80,0xbf553f6d,0xbf0e3f35,0xbe483ec4,0xbf808000,0x3f808000,0xbf808000,0x3f808000,
0x3f80,0xbf80,0x3f80,0xbf80,0xbf808000,0x3f808000,0xbf808000,0x3f808000,0x3f80,0xbf80,0x3f80,0xbf80,
0xbf808000,0x3f808000,0xbf808000,0x3f808000,0x3f80,0xbf80,0x3f80,0xbf80,0xbf808000,0x3f808000,0xbf808000,0x3f808000,
0x3f80,0xbf80,0x3f80,0xbf80,0xbe483f80,0x3f0ebf6d,0xbf553f35,0x3f7bbec4,0xbf7b8000,0x3f553ec4,0xbf0ebf35,0x3e483f6d,
0xbf7b0000,0x3f553ec4,0xbf0ebf35,0x3e483f6d,0x3e48bf80,0xbf0e3f6d,0x3f55bf35,0xbf7b3ec4,0x3e48bf80,0xbf0e3f6d,0x3f55bf35,0xbf7b3ec4,
0x3f7b8000,0xbf55bec4,0x3f0e3f35,0xbe48bf6d,0x3f7b0000,0xbf55bec4,0x3f0e3f35,0xbe48bf6d,0xbe483f80,0x3f0ebf6d,0xbf553f35,0x3f7bbec4,
0x3f6d8000,0xbec4bf35,0xbec43f80,0x3f6dbf35,0x3ec4bf80,0xbf6d3f35,0x3f6d0000,0xbec4bf35,0xbf6d8000,0x3ec43f35,0x3ec4bf80,0xbf6d3f35,
0xbec43f80,0x3f6dbf35,0xbf6d0000,0x3ec43f35,0x3f6d8000,0xbec4bf35,0xbec43f80,0x3f6dbf35,0x3ec4bf80,0xbf6d3f35,0x3f6d0000,0xbec4bf35,
0xbf6d8000,0x3ec43f35,0x3ec4bf80,0xbf6d3f35,0xbec43f80,0x3f6dbf35,0xbf6d0000,0x3ec43f35,0x3f550000,0x3e48bf6d,0xbf7b3f35,0x3f0e3ec4,
0xbf0e3f80,0x3f7bbec4,0xbe48bf35,0xbf553f6d,0xbf0e3f80,0x3f7bbec4,0xbe48bf35,0xbf553f6d,0xbf558000,0xbe483f6d,0x3f7bbf35,0xbf0ebec4,
0xbf550000,0xbe483f6d,0x3f7bbf35,0xbf0ebec4,0x3f0ebf80,0xbf7b3ec4,0x3e483f35,0x3f55bf6d,0x3f0ebf80,0xbf7b3ec4,0x3e483f35,0x3f55bf6d,
0x3f558000,0x3e48bf6d,0xbf7b3f35,0x3f0e3ec4,0xbf358000,0xbf353f80,0x3f358000,0x3f35bf80,0xbf353f80,0x3f350000,0x3f35bf80,0xbf350000,
0xbf358000,0xbf353f80,0x3f358000,0x3f35bf80,0xbf353f80,0x3f350000,0x3f35bf80,0xbf350000,0xbf358000,0xbf353f80,0x3f358000,0x3f35bf80,
0xbf353f80,0x3f350000,0x3f35bf80,0xbf350000,0xbf358000,0xbf353f80,0x3f358000,0x3f35bf80,0xbf353f80,0x3f350000,0x3f35bf80,0xbf350000,
0x3f55bf80,0xbe48bec4,0xbf7b3f35,0xbf0e3f6d,0x3f0e8000,0x3f7bbf6d,0x3e48bf35,0xbf553ec4,0x3f0e0000,0x3f7bbf6d,0x3e48bf35,0xbf553ec4,
0xbf553f80,0x3e483ec4,0x3f7bbf35,0x3f0ebf6d,0xbf553f80,0x3e483ec4,0x3f7bbf35,0x3f0ebf6d,0xbf0e8000,0xbf7b3f6d,0xbe483f35,0x3f55bec4,
0xbf0e0000,0xbf7b3f6d,0xbe483f35,0x3f55bec4,0x3f55bf80,0xbe48bec4,0xbf7b3f35,0xbf0e3f6d,0x3ec48000,0x3f6dbf35,0x3f6dbf80,0x3ec4bf35,
0x3f6dbf80,0x3ec4bf35,0xbec40000,0xbf6d3f35,0xbec48000,0xbf6d3f35,0xbf6d3f80,0xbec43f35,0xbf6d3f80,0xbec43f35,0x3ec40000,0x3f6dbf35,
0x3ec48000,0x3f6dbf35,0x3f6dbf80,0x3ec4bf35,0x3f6dbf80,0x3ec4bf35,0xbec40000,0xbf6d3f35,0xbec48000,0xbf6d3f35,0xbf6d3f80,0xbec43f35,
0xbf6d3f80,0xbec43f35,0x3ec40000,0x3f6dbf35,0xbe480000,0xbf0e3ec4,0xbf553f35,0xbf7b3f6d,0x3f7bbf80,0x3f55bf6d,0x3f0ebf35,0x3e48bec4,
0x3f7bbf80,0x3f55bf6d,0x3f0ebf35,0x3e48bec4,0x3e488000,0x3f0ebec4,0x3f55bf35,0x3f7bbf6d,0x3e480000,0x3f0ebec4,0x3f55bf35,0x3f7bbf6d,
0xbf7b3f80,0xbf553f6d,0xbf0e3f35,0xbe483ec4,0xbf7b3f80,0xbf553f6d,0xbf0e3f35,0xbe483ec4,0xbe488000,0xbf0e3ec4,0xbf553f35,0xbf7b3f6d,
0xbf803f80,0xbf803f80,0xbf803f80,0xbf803f80,0x0,0x0,0x0,0x0,0xbf803f80,0xbf803f80,0xbf803f80,0xbf803f80,
0x0,0x0,0x0,0x0,0xbf803f80,0xbf803f80,0xbf803f80,0xbf803f80,0x0,0x0,0x0,0x0,
0xbf803f80,0xbf803f80,0xbf803f80,0xbf803f80,0x0,0x0,0x0,0x0,0xbe480000,0xbf0e3ec4,0xbf553f35,0xbf7b3f6d,
0xbf7b3f80,0xbf553f6d,0xbf0e3f35,0xbe483ec4,0xbf7b3f80,0xbf553f6d,0xbf0e3f35,0xbe483ec4,0x3e480000,0x3f0ebec4,0x3f55bf35,0x3f7bbf6d,
0x3e480000,0x3f0ebec4,0x3f55bf35,0x3f7bbf6d,0x3f7bbf80,0x3f55bf6d,0x3f0ebf35,0x3e48bec4,0x3f7bbf80,0x3f55bf6d,0x3f0ebf35,0x3e48bec4,
0xbe480000,0xbf0e3ec4,0xbf553f35,0xbf7b3f6d,0x3f6dbf80,0x3ec4bf35,0xbec40000,0xbf6d3f35,0x3ec40000,0x3f6dbf35,0x3f6dbf80,0x3ec4bf35,
0xbf6d3f80,0xbec43f35,0x3ec40000,0x3f6dbf35,0xbec40000,0xbf6d3f35,0xbf6d3f80,0xbec43f35,0x3f6dbf80,0x3ec4bf35,0xbec40000,0xbf6d3f35,
0x3ec40000,0x3f6dbf35,0x3f6dbf80,0x3ec4bf35,0xbf6d3f80,0xbec43f35,0x3ec40000,0x3f6dbf35,0xbec40000,0xbf6d3f35,0xbf6d3f80,0xbec43f35,
0x3f55bf80,0xbe48bec4,0xbf7b3f35,0xbf0e3f6d,0xbf0e0000,0xbf7b3f6d,0xbe483f35,0x3f55bec4,0xbf0e0000,0xbf7b3f6d,0xbe483f35,0x3f55bec4,
0xbf553f80,0x3e483ec4,0x3f7bbf35,0x3f0ebf6d,0xbf553f80,0x3e483ec4,0x3f7bbf35,0x3f0ebf6d,0x3f0e0000,0x3f7bbf6d,0x3e48bf35,0xbf553ec4,
0x3f0e0000,0x3f7bbf6d,0x3e48bf35,0xbf553ec4,0x3f55bf80,0xbe48bec4,0xbf7b3f35,0xbf0e3f6d,0xbf353f80,0x3f350000,0x3f35bf80,0xbf350000,
0xbf350000,0xbf353f80,0x3f350000,0x3f35bf80,0xbf353f80,0x3f350000,0x3f35bf80,0xbf350000,0xbf350000,0xbf353f80,0x3f350000,0x3f35bf80,
0xbf353f80,0x3f350000,0x3f35bf80,0xbf350000,0xbf350000,0xbf353f80,0x3f350000,0x3f35bf80,0xbf353f80,0x3f350000,0x3f35bf80,0xbf350000,
0xbf350000,0xbf353f80,0x3f350000,0x3f35bf80,0x3f550000,0x3e48bf6d,0xbf7b3f35,0x3f0e3ec4,0x3f0ebf80,0xbf7b3ec4,0x3e483f35,0x3f55bf6d,
0x3f0ebf80,0xbf7b3ec4,0x3e483f35,0x3f55bf6d,0xbf550000,0xbe483f6d,0x3f7bbf35,0xbf0ebec4,0xbf550000,0xbe483f6d,0x3f7bbf35,0xbf0ebec4,
0xbf0e3f80,0x3f7bbec4,0xbe48bf35,0xbf553f6d,0xbf0e3f80,0x3f7bbec4,0xbe48bf35,0xbf553f6d,0x3f550000,0x3e48bf6d,0xbf7b3f35,0x3f0e3ec4,
0x3ec4bf80,0xbf6d3f35,0x3f6d0000,0xbec4bf35,0x3f6d0000,0xbec4bf35,0xbec43f80,0x3f6dbf35,0xbec43f80,0x3f6dbf35,0xbf6d0000,0x3ec43f35,
0xbf6d0000,0x3ec43f35,0x3ec4bf80,0xbf6d3f35,0x3ec4bf80,0xbf6d3f35,0x3f6d0000,0xbec4bf35,0x3f6d0000,0xbec4bf35,0xbec43f80,0x3f6dbf35,
0xbec43f80,0x3f6dbf35,0xbf6d0000,0x3ec43f35,0xbf6d0000,0x3ec43f35,0x3ec4bf80,0xbf6d3f35,0xbe483f80,0x3f0ebf6d,0xbf553f35,0x3f7bbec4,
0x3f7b0000,0xbf55bec4,0x3f0e3f35,0xbe48bf6d,0x3f7b0000,0xbf55bec4,0x3f0e3f35,0xbe48bf6d,0x3e48bf80,0xbf0e3f6d,0x3f55bf35,0xbf7b3ec4,
0x3e48bf80,0xbf0e3f6d,0x3f55bf35,0xbf7b3ec4,0xbf7b0000,0x3f553ec4,0xbf0ebf35,0x3e483f6d,0xbf7b0000,0x3f553ec4,0xbf0ebf35,0x3e483f6d,
0xbe483f80,0x3f0ebf6d,0xbf553f35,0x3f7bbec4,0x80008000,0x80008000,0x80008000,0x80008000,0xbf803f80,0xbf803f80,0xbf803f80,0xbf803f80,
0x80008000,0x80008000,0x80008000,0x80008000,0xbf803f80,0xbf803f80,0xbf803f80,0xbf803f80,0x80008000,0x80008000,0x80008000,0x80008000,
0xbf803f80,0xbf803f80,0xbf803f80,0xbf803f80,0x80008000,0x80008000,0x80008000,0x80008000,0xbf803f80,0xbf803f80,0xbf803f80,0xbf803f80,
0xbf7b3f80,0xbf553f6d,0xbf0e3f35,0xbe483ec4,0x3e488000,0x3f0ebec4,0x3f55bf35,0x3f7bbf6d,0x3e480000,0x3f0ebec4,0x3f55bf35,0x3f7bbf6d,
0x3f7bbf80,0x3f55bf6d,0x3f0ebf35,0x3e48bec4,0x3f7bbf80,0x3f55bf6d,0x3f0ebf35,0x3e48bec4,0xbe488000,0xbf0e3ec4,0xbf553f35,0xbf7b3f6d,
0xbe480000,0xbf0e3ec4,0xbf553f35,0xbf7b3f6d,0xbf7b3f80,0xbf553f6d,0xbf0e3f35,0xbe483ec4,0xbec48000,0xbf6d3f35,0xbf6d3f80,0xbec43f35,
0x3f6dbf80,0x3ec4bf35,0xbec40000,0xbf6d3f35,0x3ec48000,0x3f6dbf35,0x3f6dbf80,0x3ec4bf35,0xbf6d3f80,0xbec43f35,0x3ec40000,0x3f6dbf35,
0xbec48000,0xbf6d3f35,0xbf6d3f80,0xbec43f35,0x3f6dbf80,0x3ec4bf35,0xbec40000,0xbf6d3f35,0x3ec48000,0x3f6dbf35,0x3f6dbf80,0x3ec4bf35,
0xbf6d3f80,0xbec43f35,0x3ec40000,0x3f6dbf35,0xbf0e0000,0xbf7b3f6d,0xbe483f35,0x3f55bec4,0xbf553f80,0x3e483ec4,0x3f7bbf35,0x3f0ebf6d,
0xbf553f80,0x3e483ec4,0x3f7bbf35,0x3f0ebf6d,0x3f0e8000,0x3f7bbf6d,0x3e48bf35,0xbf553ec4,0x3f0e0000,0x3f7bbf6d,0x3e48bf35,0xbf553ec4,
0x3f55bf80,0xbe48bec4,0xbf7b3f35,0xbf0e3f6d,0x3f55bf80,0xbe48bec4,0xbf7b3f35,0xbf0e3f6d,0xbf0e8000,0xbf7b3f6d,0xbe483f35,0x3f55bec4,
0x3f358000,0x3f35bf80,0xbf358000,0xbf353f80,0xbf353f80,0x3f350000,0x3f35bf80,0xbf350000,0x3f358000,0x3f35bf80,0xbf358000,0xbf353f80,
0xbf353f80,0x3f350000,0x3f35bf80,0xbf350000,0x3f358000,0x3f35bf80,0xbf358000,0xbf353f80,0xbf353f80,0x3f350000,0x3f35bf80,0xbf350000,
0x3f358000,0x3f35bf80,0xbf358000,0xbf353f80,0xbf353f80,0x3f350000,0x3f35bf80,0xbf350000,0x3f0ebf80,0xbf7b3ec4,0x3e483f35,0x3f55bf6d,
0xbf558000,0xbe483f6d,0x3f7bbf35,0xbf0ebec4,0xbf550000,0xbe483f6d,0x3f7bbf35,0xbf0ebec4,0xbf0e3f80,0x3f7bbec4,0xbe48bf35,0xbf553f6d,
0xbf0e3f80,0x3f7bbec4,0xbe48bf35,0xbf553f6d,0x3f558000,0x3e48bf6d,0xbf7b3f35,0x3f0e3ec4,0x3f550000,0x3e48bf6d,0xbf7b3f35,0x3f0e3ec4,
0x3f0ebf80,0xbf7b3ec4,0x3e483f35,0x3f55bf6d,0xbf6d8000,0x3ec43f35,0x3ec4bf80,0xbf6d3f35,0x3ec4bf80,0xbf6d3f35,0x3f6d0000,0xbec4bf35,
0x3f6d8000,0xbec4bf35,0xbec43f80,0x3f6dbf35,0xbec43f80,0x3f6dbf35,0xbf6d0000,0x3ec43f35,0xbf6d8000,0x3ec43f35,0x3ec4bf80,0xbf6d3f35,
0x3ec4bf80,0xbf6d3f35,0x3f6d0000,0xbec4bf35,0x3f6d8000,0xbec4bf35,0xbec43f80,0x3f6dbf35,0xbec43f80,0x3f6dbf35,0xbf6d0000,0x3ec43f35,
0x3f7b0000,0xbf55bec4,0x3f0e3f35,0xbe48bf6d,0x3e48bf80,0xbf0e3f6d,0x3f55bf35,0xbf7b3ec4,0x3e48bf80,0xbf0e3f6d,0x3f55bf35,0xbf7b3ec4,
0xbf7b8000,0x3f553ec4,0xbf0ebf35,0x3e483f6d,0xbf7b0000,0x3f553ec4,0xbf0ebf35,0x3e483f6d,0xbe483f80,0x3f0ebf6d,0xbf553f35,0x3f7bbec4,
0xbe483f80,0x3f0ebf6d,0xbf553f35,0x3f7bbec4,0x3f7b8000,0xbf55bec4,0x3f0e3f35,0xbe48bf6d,0x3f80,0xbf80,0x3f80,0xbf80,
0xbf800000,0x3f800000,0xbf800000,0x3f800000,0x3f80,0xbf80,0x3f80,0xbf80,0xbf800000,0x3f800000,0xbf800000,0x3f800000,
0x3f80,0xbf80,0x3f80,0xbf80,0xbf800000,0x3f800000,0xbf800000,0x3f800000,0x3f80,0xbf80,0x3f80,0xbf80,
0xbf800000,0x3f800000,0xbf800000,0x3f800000,0xbf7b0000,0x3f55bec4,0xbf0e3f35,0x3e48bf6d,0x3e483f80,0xbf0ebf6d,0x3f553f35,0xbf7bbec4,
0x3e483f80,0xbf0ebf6d,0x3f553f35,0xbf7bbec4,0x3f7b0000,0xbf553ec4,0x3f0ebf35,0xbe483f6d,0x3f7b0000,0xbf553ec4,0x3f0ebf35,0xbe483f6d,
0xbe48bf80,0x3f0e3f6d,0xbf55bf35,0x3f7b3ec4,0xbe48bf80,0x3f0e3f6d,0xbf55bf35,0x3f7b3ec4,0xbf7b0000,0x3f55bec4,0xbf0e3f35,0x3e48bf6d,
0xbec4bf80,0x3f6d3f35,0xbf6d0000,0x3ec4bf35,0x3f6d0000,0xbec43f35,0xbec4bf80,0x3f6d3f35,0x3ec43f80,0xbf6dbf35,0x3f6d0000,0xbec43f35,
0xbf6d0000,0x3ec4bf35,0x3ec43f80,0xbf6dbf35,0xbec4bf80,0x3f6d3f35,0xbf6d0000,0x3ec4bf35,0x3f6d0000,0xbec43f35,0xbec4bf80,0x3f6d3f35,
0x3ec43f80,0xbf6dbf35,0x3f6d0000,0xbec43f35,0xbf6d0000,0x3ec4bf35,0x3ec43f80,0xbf6dbf35,0xbf0ebf80,0x3f7b3ec4,0xbe483f35,0xbf55bf6d,
0xbf550000,0xbe48bf6d,0x3f7b3f35,0xbf0e3ec4,0xbf550000,0xbe48bf6d,0x3f7b3f35,0xbf0e3ec4,0x3f0e3f80,0xbf7bbec4,0x3e48bf35,0x3f553f6d,
0x3f0e3f80,0xbf7bbec4,0x3e48bf35,0x3f553f6d,0x3f550000,0x3e483f6d,0xbf7bbf35,0x3f0ebec4,0x3f550000,0x3e483f6d,0xbf7bbf35,0x3f0ebec4,
0xbf0ebf80,0x3f7b3ec4,0xbe483f35,0xbf55bf6d,0x3f353f80,0xbf350000,0xbf35bf80,0x3f350000,0xbf350000,0xbf35bf80,0x3f350000,0x3f353f80,
0x3f353f80,0xbf350000,0xbf35bf80,0x3f350000,0xbf350000,0xbf35bf80,0x3f350000,0x3f353f80,0x3f353f80,0xbf350000,0xbf35bf80,0x3f350000,
0xbf350000,0xbf35bf80,0x3f350000,0x3f353f80,0x3f353f80,0xbf350000,0xbf35bf80,0x3f350000,0xbf350000,0xbf35bf80,0x3f350000,0x3f353f80,
0x3f0e0000,0x3f7b3f6d,0x3e483f35,0xbf55bec4,0xbf55bf80,0x3e48bec4,0x3f7b3f35,0x3f0e3f6d,0xbf55bf80,0x3e48bec4,0x3f7b3f35,0x3f0e3f6d,
0xbf0e0000,0xbf7bbf6d,0xbe48bf35,0x3f553ec4,0xbf0e0000,0xbf7bbf6d,0xbe48bf35,0x3f553ec4,0x3f553f80,0xbe483ec4,0xbf7bbf35,0xbf0ebf6d,
0x3f553f80,0xbe483ec4,0xbf7bbf35,0xbf0ebf6d,0x3f0e0000,0x3f7b3f6d,0x3e483f35,0xbf55bec4,0xbf6dbf80,0xbec4bf35,0x3ec40000,0x3f6d3f35,
0x3ec40000,0x3f6d3f35,0x3f6d3f80,0x3ec43f35,0x3f6d3f80,0x3ec43f35,0xbec40000,0xbf6dbf35,0xbec40000,0xbf6dbf35,0xbf6dbf80,0xbec4bf35,
0xbf6dbf80,0xbec4bf35,0x3ec40000,0x3f6d3f35,0x3ec40000,0x3f6d3f35,0x3f6d3f80,0x3ec43f35,0x3f6d3f80,0x3ec43f35,0xbec40000,0xbf6dbf35,
0xbec40000,0xbf6dbf35,0xbf6dbf80,0xbec4bf35,0x3f7b3f80,0x3f553f6d,0x3f0e3f35,0x3e483ec4,0x3e480000,0x3f0e3ec4,0x3f553f35,0x3f7b3f6d,
0x3e480000,0x3f0e3ec4,0x3f553f35,0x3f7b3f6d,0xbf7bbf80,0xbf55bf6d,0xbf0ebf35,0xbe48bec4,0xbf7bbf80,0xbf55bf6d,0xbf0ebf35,0xbe48bec4,
0xbe480000,0xbf0ebec4,0xbf55bf35,0xbf7bbf6d,0xbe480000,0xbf0ebec4,0xbf55bf35,0xbf7bbf6d,0x3f7b3f80,0x3f553f6d,0x3f0e3f35,0x3e483ec4,
0x3f808000,0xbf808000,0x3f808000,0xbf808000,0x3f80,0xbf80,0x3f80,0xbf80,0x3f808000,0xbf808000,0x3f808000,0xbf808000,
0x3f80,0xbf80,0x3f80,0xbf80,0x3f808000,0xbf808000,0x3f808000,0xbf808000,0x3f80,0xbf80,0x3f80,0xbf80,
0x3f808000,0xbf808000,0x3f808000,0xbf808000,0x3f80,0xbf80,0x3f80,0xbf80,0x3e483f80,0xbf0ebf6d,0x3f553f35,0xbf7bbec4,
0x3f7b8000,0xbf553ec4,0x3f0ebf35,0xbe483f6d,0x3f7b0000,0xbf553ec4,0x3f0ebf35,0xbe483f6d,0xbe48bf80,0x3f0e3f6d,0xbf55bf35,0x3f7b3ec4,
0xbe48bf80,0x3f0e3f6d,0xbf55bf35,0x3f7b3ec4,0xbf7b8000,0x3f55bec4,0xbf0e3f35,0x3e48bf6d,0xbf7b0000,0x3f55bec4,0xbf0e3f35,0x3e48bf6d,
0x3e483f80,0xbf0ebf6d,0x3f553f35,0xbf7bbec4,0xbf6d8000,0x3ec4bf35,0x3ec43f80,0xbf6dbf35,0xbec4bf80,0x3f6d3f35,0xbf6d0000,0x3ec4bf35,
0x3f6d8000,0xbec43f35,0xbec4bf80,0x3f6d3f35,0x3ec43f80,0xbf6dbf35,0x3f6d0000,0xbec43f35,0xbf6d8000,0x3ec4bf35,0x3ec43f80,0xbf6dbf35,
0xbec4bf80,0x3f6d3f35,0xbf6d0000,0x3ec4bf35,0x3f6d8000,0xbec43f35,0xbec4bf80,0x3f6d3f35,0x3ec43f80,0xbf6dbf35,0x3f6d0000,0xbec43f35,
0xbf550000,0xbe48bf6d,0x3f7b3f35,0xbf0e3ec4,0x3f0e3f80,0xbf7bbec4,0x3e48bf35,0x3f553f6d,0x3f0e3f80,0xbf7bbec4,0x3e48bf35,0x3f553f6d,
0x3f558000,0x3e483f6d,0xbf7bbf35,0x3f0ebec4,0x3f550000,0x3e483f6d,0xbf7bbf35,0x3f0ebec4,0xbf0ebf80,0x3f7b3ec4,0xbe483f35,0xbf55bf6d,
0xbf0ebf80,0x3f7b3ec4,0xbe483f35,0xbf55bf6d,0xbf558000,0xbe48bf6d,0x3f7b3f35,0xbf0e3ec4,0x3f358000,0x3f353f80,0xbf358000,0xbf35bf80,
0x3f353f80,0xbf350000,0xbf35bf80,0x3f350000,0x3f358000,0x3f353f80,0xbf358000,0xbf35bf80,0x3f353f80,0xbf350000,0xbf35bf80,0x3f350000,
0x3f358000,0x3f353f80,0xbf358000,0xbf35bf80,0x3f353f80,0xbf350000,0xbf35bf80,0x3f350000,0x3f358000,0x3f353f80,0xbf358000,0xbf35bf80,
0x3f353f80,0xbf350000,0xbf35bf80,0x3f350000,0xbf55bf80,0x3e48bec4,0x3f7b3f35,0x3f0e3f6d,0xbf0e8000,0xbf7bbf6d,0xbe48bf35,0x3f553ec4,
0xbf0e0000,0xbf7bbf6d,0xbe48bf35,0x3f553ec4,0x3f553f80,0xbe483ec4,0xbf7bbf35,0xbf0ebf6d,0x3f553f80,0xbe483ec4,0xbf7bbf35,0xbf0ebf6d,
0x3f0e8000,0x3f7b3f6d,0x3e483f35,0xbf55bec4,0x3f0e0000,0x3f7b3f6d,0x3e483f35,0xbf55bec4,0xbf55bf80,0x3e48bec4,0x3f7b3f35,0x3f0e3f6d,
0xbec48000,0xbf6dbf35,0xbf6dbf80,0xbec4bf35,0xbf6dbf80,0xbec4bf35,0x3ec40000,0x3f6d3f35,0x3ec48000,0x3f6d3f35,0x3f6d3f80,0x3ec43f35,
0x3f6d3f80,0x3ec43f35,0xbec40000,0xbf6dbf35,0xbec48000,0xbf6dbf35,0xbf6dbf80,0xbec4bf35,0xbf6dbf80,0xbec4bf35,0x3ec40000,0x3f6d3f35,
0x3ec48000,0x3f6d3f35,0x3f6d3f80,0x3ec43f35,0x3f6d3f80,0x3ec43f35,0xbec40000,0xbf6dbf35,0x3e480000,0x3f0e3ec4,0x3f553f35,0x3f7b3f6d,
0xbf7bbf80,0xbf55bf6d,0xbf0ebf35,0xbe48bec4,0xbf7bbf80,0xbf55bf6d,0xbf0ebf35,0xbe48bec4,0xbe488000,0xbf0ebec4,0xbf55bf35,0xbf7bbf6d,
0xbe480000,0xbf0ebec4,0xbf55bf35,0xbf7bbf6d,0x3f7b3f80,0x3f553f6d,0x3f0e3f35,0x3e483ec4,0x3f7b3f80,0x3f553f6d,0x3f0e3f35,0x3e483ec4,
0x3e488000,0x3f0e3ec4,0x3f553f35,0x3f7b3f6d,0x3f803f80,0x80008000,0x3f803f80,0x80008000,0x3f803f80,0x80008000,0x3f803f80,0x80008000,
0x3f803f80,0x80008000,0x3f803f80,0x80008000,0x3f803f80,0x80008000,0x3f803f80,0x80008000,0x3f803f80,0xbbc98000,0x3f803f80,0xbd62bd49,
0x3f803f80,0xbc97bc49,0x3f7f3f80,0xbd8abd7b,0x3f803f80,0xbcfbbcc9,0x3f7f3f7f,0xbda3bd97,0x3f803f80,0xbd30bd17,0x3f7f3f7f,0xbdbcbdb0,
0x3f803f80,0xbc498000,0x3f7e3f7f,0xbde2bdc9,0x3f803f80,0xbd17bcc9,0x3f7e3f7e,0xbe0abdfb,0x3f803f80,0xbd7bbd49,0x3f7d3f7d,0xbe23be16,
0x3f7f3f7f,0xbdb0bd97,0x3f7c3f7c,0xbe3bbe2f,0x3f803f80,0xbc978000,0x3f7c3f7d,0xbe29be16,0x3f803f80,0xbd62bd17,0x3f7b3f7c,0xbe4ebe3b,
0x3f7f3f7f,0xbdbcbd97,0x3f793f7a,0xbe73be60,0x3f7e3f7e,0xbe04bde2,0x3f763f78,0xbe8cbe82,0x3f803f80,0xbcc98000,0x3f7a3f7b,0xbe60be48,
0x3f7f3f80,0xbd97bd49,0x3f773f78,0xbe89be79,0x3f7e3f7f,0xbdfbbdc9,0x3f733f75,0xbea1be95,0x3f7c3f7d,0xbe2fbe16,0x3f6f3f71,0xbeb8beac,
0x3f803f80,0xbcfb8000,0x3f763f78,0xbe8cbe79,0x3f7f3f80,0xbdbcbd7b,0x3f723f74,0xbeaabe9b,0x3f7d3f7e,0xbe1cbdfb,0x3f6c3f6f,0xbec7beb8,
0x3f7a3f7c,0xbe5abe3b,0x3f653f69,0xbee3bed5,0x3f803f80,0xbd178000,0x3f723f75,0xbea7be95,0x3f7e3f7f,0xbde2bd97,0x3f6b3f6f,0xbecabeb8,
0x3f7c3f7d,0xbe3bbe16,0x3f633f67,0xbeecbedb,0x3f783f7a,0xbe82be60,0x3f5a3f5f,0xbf06befc,0x3f803f80,0xbd308000,0x3f6d3f71,0xbec1beac,
0x3f7e3f7f,0xbe04bdb0,0x3f643f69,0xbee9bed5,0x3f7a3f7c,0xbe5abe2f,0x3f593f5f,0xbf08befc,0x3f753f78,0xbe98be82,0x3f4d3f53,0xbf1abf11,
0x3f803f80,0xbd498000,0x3f673f6d,0xbedbbec4,0x3f7d3f7f,0xbe16bdc9,0x3f5c3f62,0xbf04bef1,0x3f783f7b,0xbe79be48,0x3f4e3f55,0xbf18bf0e,
0x3f713f75,0xbeacbe95,0x3f3e3f46,0xbf2cbf22,0x3f803f80,0xbd628000,0x3f613f67,0xbef4bedb,0x3f7c3f7e,0xbe29bde2,0x3f523f5a,0xbf12bf06,
0x3f763f7a,0xbe8cbe60,0x3f413f4a,0xbf28bf1d,0x3f6d3f72,0xbec1bea7,0x3f2d3f37,0xbf3dbf33,0x3f803f80,0xbd7b8000,0x3f5a3f62,0xbf06bef1,
0x3f7c3f7e,0xbe3bbdfb,0x3f483f51,0xbf20bf13,0x3f743f78,0xbe9bbe79,0x3f333f3e,0xbf37bf2c,0x3f693f6f,0xbed5beb8,0x3f1b3f27,0xbf4cbf42,
0x3f7f3f80,0xbd8a8000,0x3f523f5c,0xbf12bf04,0x3f7b3f7e,0xbe4ebe0a,0x3f3d3f48,0xbf2dbf20,0x3f723f77,0xbeaabe89,0x3f243f31,0xbf45bf39,
0x3f643f6b,0xbee9beca,0x3f083f16,0xbf59bf4f,0x3f7f3f80,0xbd978000,0x3f4a3f55,0xbf1dbf0e,0x3f7a3f7d,0xbe60be16,0x3f313f3e,0xbf39bf2c,
0x3f6f3f75,0xbeb8be95,0x3f133f22,0xbf51bf46,0x3f5f3f67,0xbefcbedb,0x3ee63f04,0xbf65bf5c,0x3f7f3f80,0xbda38000,0x3f413f4e,0xbf28bf18,
0x3f793f7d,0xbe73be23,0x3f243f33,0xbf45bf37,0x3f6c3f73,0xbec7bea1,0x3f023f13,0xbf5cbf51,0x3f593f63,0xbf08beec,0x3ebb3ee1,0xbf6ebf66,
0x3f7f3f80,0xbdb08000,0x3f373f46,0xbf33bf22,0x3f783f7c,0xbe82be2f,0x3f163f27,0xbf4fbf42,0x3f693f71,0xbed5beac,0x3ee13f04,0xbf66bf5c,
0x3f533f5f,0xbf11befc,0x3e8f3eb8,0xbf76bf6f,0x3f7f3f80,0xbdbc8000,0x3f2d3f3e,0xbf3dbf2c,0x3f763f7c,0xbe8cbe3b,0x3f083f1b,0xbf59bf4c,
0x3f653f6f,0xbee3beb8,0x3ebb3ee6,0xbf6ebf65,0x3f4d3f5a,0xbf1abf06,0x3e423e8f,0xbf7bbf76,0x3f7f3f80,0xbdc98000,0x3f223f35,0xbf46bf35,
0x3f753f7b,0xbe95be48,0x3ef13f0e,0xbf62bf55,0x3f623f6d,0xbef1bec4,0x3e953ec4,0xbf75bf6d,0x3f463f55,0xbf22bf0e,0x3dc93e48,0xbf7fbf7b,
0x3f7f3f80,0xbdd58000,0x3f173f2c,0xbf4fbf3e,0x3f743f7a,0xbe9ebe54,0x3ed23f01,0xbf69bf5d,0x3f5e3f6a,0xbeffbecf,0x3e5a3ea1,0xbf7abf73,
0x3f3f3f4f,0xbf2bbf16,0x3bc93de2,0xbf80bf7e,0x3f7e3f80,0xbde28000,0x3f0c3f22,0xbf57bf46,0x3f723f7a,0xbea7be60,0x3eb23ee6,0xbf70bf65,
0x3f5a3f67,0xbf06bedb,0x3e0a3e79,0xbf7ebf78,0x3f373f4a,0xbf33bf1d,0xbdb03cc9,0xbf7fbf80,0x3f7e3f80,0xbdee8000,0x3eff3f18,0xbf5ebf4e,
0x3f713f79,0xbeafbe6d,0x3e923eca,0xbf75bf6b,0x3f563f65,0xbf0dbee6,0x3d623e2f,0xbf80bf7c,0x3f2f3f44,0xbf3abf25,0xbe35bd7b,0xbf7cbf80,
0x3f7e3f80,0xbdfb8000,0x3ee63f0e,0xbf65bf55,0x3f6f3f78,0xbeb8be79,0x3e603eac,0xbf7abf71,0x3f513f62,0xbf13bef1,0xbcc93dc9,0xbf80bf7f,
0x3f273f3e,0xbf42bf2c,0xbe89be16,0xbf77bf7d,0x3f7e3f80,0xbe048000,0x3ecd3f04,0xbf6bbf5c,0x3f6d3f78,0xbec1be82,0x3e1c3e8f,0xbf7dbf76,
0x3f4d3f5f,0xbf1abefc,0xbdd53cc9,0xbf7fbf80,0x3f1f3f37,0xbf49bf33,0xbeb5be6d,0xbf6fbf79,0x3f7e3f80,0xbe0a8000,0x3eb23ef1,0xbf70bf62,
0x3f6b3f77,0xbecabe89,0x3db03e60,0xbf7fbf7a,0x3f483f5c,0xbf20bf04,0xbe3bbd49,0xbf7cbf80,0x3f163f31,0xbf4fbf39,0xbee1bea1,0xbf66bf73,
0x3f7d3f80,0xbe108000,0x3e983edb,0xbf75bf67,0x3f693f76,0xbed2be8f,0x3c973e23,0xbf80bf7d,0x3f433f58,0xbf26bf09,0xbe86bdfb,0xbf77bf7e,
0x3f0d3f2a,0xbf56bf40,0xbf05beca,0xbf5bbf6b,0x3f7d3f80,0xbe168000,0x3e793ec4,0xbf78bf6d,0x3f673f75,0xbedbbe95,0xbd493dc9,0xbf80bf7f,
0x3f3e3f55,0xbf2cbf0e,0xbeacbe48,0xbf71bf7b,0x3f043f22,0xbf5cbf46,0xbf18bef1,0xbf4ebf62,0x3f7d3f80,0xbe1c8000,0x3e423eac,0xbf7bbf71,
0x3f653f74,0xbee3be9b,0xbdee3d17,0xbf7ebf80,0x3f383f51,0xbf32bf13,0xbed2be89,0xbf69bf77,0x3ef43f1b,0xbf61bf4c,0xbf2bbf0c,0xbf3fbf57,
0x3f7d3f80,0xbe238000,0x3e0a3e95,0xbf7ebf75,0x3f633f73,0xbeecbea1,0xbe3bbcc9,0xbf7cbf80,0x3f333f4e,0xbf37bf18,0xbef7beac,0xbf60bf71,
0x3ee13f13,0xbf66bf51,0xbf3cbf1d,0xbf2ebf4a,0x3f7c3f80,0xbe298000,0x3da33e79,0xbf7fbf78,0x3f613f72,0xbef4bea7,0xbe7fbdb0,0xbf78bf7f,
0x3f2d3f4a,0xbf3dbf1d,0xbf0dbecf,0xbf56bf6a,0x3ecd3f0c,0xbf6bbf57,0xbf4bbf2e,0xbf1cbf3c,0x3f7c3f80,0xbe2f8000,0x3cc93e48,0xbf80bf7b,
0x3f5f3f71,0xbefcbeac,0xbea1be16,0xbf73bf7d,0x3f273f46,0xbf42bf22,0xbf1dbef1,0xbf4abf62,0x3eb83f04,0xbf6fbf5c,0xbf58bf3e,0xbf09bf2c,
0x3f7c3f80,0xbe358000,0xbcfb3e16,0xbf80bf7d,0x3f5c3f70,0xbf02beb2,0xbec1be54,0xbf6dbf7a,0x3f213f42,0xbf47bf27,0xbf2dbf09,0xbf3dbf58,
0x3ea43ef7,0xbf73bf60,0xbf64bf4c,0xbee9bf1b,0x3f7c3f80,0xbe3b8000,0xbdb03dc9,0xbf7fbf7f,0x3f5a3f6f,0xbf06beb8,0xbee1be89,0xbf66bf77,
0x3f1b3f3e,0xbf4cbf2c,0xbf3cbf18,0xbf2ebf4e,0x3e8f3ee6,0xbf76bf65,0xbf6ebf58,0xbebebf09,0x3f7b3f80,0xbe428000,0xbe103d49,0xbf7dbf80,
0x3f573f6e,0xbf0abebe,0xbeffbea7,0xbf5ebf72,0x3f153f39,0xbf50bf31,0xbf49bf27,0xbf1fbf42,0x3e733ed5,0xbf79bf69,0xbf75bf63,0xbe92beec,
0x3f803f80,0x80008000,0x3f803f80,0x80008000,0x3f803f80,0x80008000,0x3f803f80,0x80008000,0x3f803f80,0x80008000,0x3f803f80,0x80008000,
0x3f803f80,0x80008000,0x3f803f80,0x80008000,0x3f7f3f7f,0xbdd5bdc9,0x3f7d3f7d,0xbe1cbe16,0x3f7e3f7e,0xbdeebde2,0x3f7c3f7d,0xbe29be23,
0x3f7e3f7e,0xbe04bdfb,0x3f7c3f7c,0xbe35be2f,0x3f7d3f7e,0xbe10be0a,0x3f7b3f7c,0xbe42be3b,0x3f7a3f7b,0xbe54be48,0x3f743f75,0xbe9bbe95,
0x3f793f7a,0xbe6dbe60,0x3f723f73,0xbea7bea1,0x3f783f78,0xbe82be79,0x3f703f71,0xbeb2beac,0x3f763f77,0xbe8fbe89,0x3f6e3f6f,0xbebebeb8,
0x3f743f75,0xbe9ebe95,0x3f653f67,0xbee3bedb,0x3f713f72,0xbeafbea7,0x3f613f63,0xbef4beec,0x3f6d3f6f,0xbec1beb8,0x3f5c3f5f,0xbf02befc,
0x3f693f6b,0xbed2beca,0x3f573f5a,0xbf0abf06,0x3f6a3f6d,0xbecfbec4,0x3f513f55,0xbf13bf0e,0x3f653f67,0xbee6bedb,0x3f4a3f4e,0xbf1dbf18,
0x3f5f3f62,0xbefcbef1,0x3f423f46,0xbf27bf22,0x3f583f5c,0xbf09bf04,0x3f393f3e,0xbf31bf2c,0x3f5e3f62,0xbeffbef1,0x3f383f3e,0xbf32bf2c,
0x3f563f5a,0xbf0dbf06,0x3f2d3f33,0xbf3dbf37,0x3f4d3f51,0xbf1abf13,0x3f213f27,0xbf47bf42,0x3f433f48,0xbf26bf20,0x3f153f1b,0xbf50bf4c,
0x3f4f3f55,0xbf16bf0e,0x3f1b3f22,0xbf4cbf46,0x3f443f4a,0xbf25bf1d,0x3f0c3f13,0xbf57bf51,0x3f373f3e,0xbf33bf2c,0x3ef73f04,0xbf60bf5c,
0x3f2a3f31,0xbf40bf39,0x3ed53ee6,0xbf69bf65,0x3f3f3f46,0xbf2bbf22,0x3ef43f04,0xbf61bf5c,0x3f2f3f37,0xbf3abf33,0x3ecd3ee1,0xbf6bbf66,
0x3f1f3f27,0xbf49bf42,0x3ea43eb8,0xbf73bf6f,0x3f0d3f16,0xbf56bf4f,0x3e733e8f,0xbf79bf76,0x3f2c3f35,0xbf3ebf35,0x3eac3ec4,0xbf71bf6d,
0x3f183f22,0xbf4ebf46,0x3e793e95,0xbf78bf75,0x3f043f0e,0xbf5cbf55,0x3e163e48,0xbf7dbf7b,0x3edb3ef1,0xbf67bf62,0x3d493dc9,0xbf80bf7f,
0x3f173f22,0xbf4fbf46,0x3e423e79,0xbf7bbf78,0x3eff3f0c,0xbf5ebf57,0x3da33e0a,0xbf7fbf7e,0x3ecd3ee6,0xbf6bbf65,0xbcfb3cc9,0xbf80bf80,
0x3e983eb2,0xbf75bf70,0xbe10bdb0,0xbf7dbf7f,0x3f013f0e,0xbf5dbf55,0x3d173dc9,0xbf80bf7f,0x3eca3ee6,0xbf6bbf65,0xbdb0bcc9,0xbf7fbf80,
0x3e8f3eac,0xbf76bf71,0xbe54be16,0xbf7abf7d,0x3e233e60,0xbf7dbf7a,0xbea7be89,0xbf72bf77,0x3ed23ef1,0xbf69bf62,0xbdeebd49,0xbf7ebf80,
0x3e923eb2,0xbf75bf70,0xbe7fbe3b,0xbf78bf7c,0x3e1c3e60,0xbf7dbf7a,0xbec1bea1,0xbf6dbf73,0x3c973db0,0xbf80bf7f,0xbeffbee1,0xbf5ebf66,
0x3ea13ec4,0xbf73bf6d,0xbe89be48,0xbf77bf7b,0x3e2f3e79,0xbf7cbf78,0xbecfbeac,0xbf6abf71,0x3cc93dc9,0xbf80bf7f,0xbf09bef1,0xbf58bf62,
0xbdfbbd49,0xbf7ebf80,0xbf27bf18,0xbf42bf4e,0x3e5a3e95,0xbf7abf75,0xbed2beac,0xbf69bf71,0x3d623e0a,0xbf80bf7e,0xbf0dbef7,0xbf56bf60,
0xbdd5bcc9,0xbf7fbf80,0xbf2dbf1d,0xbf3dbf4a,0xbe86be3b,0xbf77bf7c,0xbf49bf3c,0xbf1fbf2e,0x3de23e48,0xbf7ebf7b,0xbf0cbef1,0xbf57bf62,
0xbd7b3cc9,0xbf80bf80,0xbf2ebf1d,0xbf3cbf4a,0xbe6dbe16,0xbf79bf7d,0xbf4cbf3e,0xbf1bbf2c,0xbecabea1,0xbf6bbf73,0xbf63bf58,0xbeecbf09,
0x3bc93dc9,0xbf80bf7f,0xbf2bbf18,0xbf3fbf4e,0xbe35bdb0,0xbf7cbf7f,0xbf4bbf3c,0xbf1cbf2e,0xbeb5be89,0xbf6fbf77,0xbf64bf58,0xbee9bf09,
0xbf05bee1,0xbf5bbf66,0xbf75bf6e,0xbe92bebe,0xbdc90000,0xbf7fbf80,0xbf46bf35,0xbf22bf35,0xbe95be48,0xbf75bf7b,0xbf62bf55,0xbef1bf0e,
0xbef1bec4,0xbf62bf6d,0xbf75bf6d,0xbe95bec4,0xbf22bf0e,0xbf46bf55,0xbf7fbf7b,0xbdc9be48,0xbe4ebdc9,0xbf7bbf7f,0xbf5cbf4e,0xbf02bf18,
0xbecdbe9b,0xbf6bbf74,0xbf73bf69,0xbea4bed5,0xbf15befc,0xbf50bf5f,0xbf7ebf7a,0xbdeebe60,0xbf3dbf2a,0xbf2dbf40,0xbf7fbf80,0x3dbcbc49,
0xbe9bbe48,0xbf74bf7b,0xbf6ebf62,0xbebebef1,0xbf01becf,0xbf5dbf6a,0xbf7dbf77,0xbe23be89,0xbf2ebf18,0xbf3cbf4e,0xbf80bf80,0x3d7bbd49,
0xbf53bf42,0xbf11bf27,0xbf76bf7c,0x3e8f3e2f,0xbecdbe95,0xbf6bbf75,0xbf79bf71,0xbe66beac,0xbf1abf01,0xbf4dbf5d,0xbf80bf7e,0x3bc9bde2,
0xbf45bf31,0xbf24bf39,0xbf79bf7e,0x3e733dfb,0xbf65bf57,0xbee3bf0c,0xbf64bf70,0x3ee93eb2,0xbefcbec4,0xbf5fbf6d,0xbf7fbf7b,0xbd97be48,
0xbf31bf18,0xbf39bf4e,0xbf7cbf80,0x3e2f3d49,0xbf58bf46,0xbf09bf22,0xbf6abf75,0x3ecf3e95,0xbf73bf67,0xbea1bedb,0xbf4abf5c,0x3f1d3f04,
0xbf15bef1,0xbf50bf62,0xbf7fbf80,0x3da3bd49,0xbf45bf2e,0xbf24bf3c,0xbf72bf7a,0x3eaa3e54,0xbf68bf58,0xbed8bf09,0xbf54bf65,0x3f103ee6,
0xbf7cbf74,0xbe35be9b,0xbf28bf40,0x3f413f2a,0xbf2abf0e,0xbf40bf55,0xbf79bf7f,0x3e6d3dc9,0xbf57bf42,0xbf0cbf27,0xbf60bf6f,0x3ef73eb8,
0xbf74bf67,0xbe9bbedb,0xbf37bf4e,0x3f333f18,0xbf80bf7c,0xbd17be2f,0xbf01bf1d,0x3f5d3f4a,0xbf3dbf22,0xbf2dbf46,0xbf6dbf78,0x3ec13e79,
0xbf65bf53,0xbee3bf11,0xbf49bf5d,0x3f1f3f01,0xbf7cbf73,0xbe35bea1,0xbf15bf31,0x3f503f39,0xbf7fbf80,0x3dd5bd17,0xbeaabeec,0x3f723f63,
0xbf4ebf35,0xbf18bf35,0xbf5cbf6d,0x3f043ec4,0xbf71bf62,0xbeacbef1,0xbf2cbf46,0x3f3e3f22,0xbf80bf7b,0xbd49be48,0xbedbbf0e,0x3f673f55,
0xbf78bf7f,0x3e793dc9,0xbe16be95,0x3f7d3f75,0xbf5cbf46,0xbf02bf22,0xbf45bf5c,0x3f243f04,0xbf79bf6e,0xbe66bebe,0xbf0abf2a,0x3f573f40,
0xbf7fbf7f,0x3da3bd97,0xbe86becf,0x3f773f6a,0xbf6dbf79,0x3ec13e6d,0x3d30bde2,0x3f803f7e,0xbf69bf55,0xbed5bf0e,0xbf2abf46,0x3f403f22,
0xbf7ebf77,0xbde2be89,0xbecabf09,0x3f6b3f58,0xbf7abf80,0x3e543d49,0xbdb0be79,0x3f7f3f78,0xbf5dbf6f,0x3f013eb8,0x3e6d3d97,0x3f793f7f,
0xbf73bf62,0xbea4bef1,0xbf0abf2c,0x3f573f3e,0xbf80bf7d,0x3bc9be23,0xbe73beca,0x3f793f6b,0xbf72bf7c,0x3eaa3e2f,0x3dbcbd97,0x3f7f3f7f,
0xbf49bf60,0x3f1f3ef7,0x3ed23e82,0x3f693f78,0xbf7abf6d,0xbe60bec4,0xbecfbf0e,0x3f6a3f55,0xbf7ebf80,0x3dfbbd49,0xbd97be79,0x3f7f3f78,
0xbf65bf75,0x3ee63e95,0x3e893dc9,0x3f773f7f,0xbf31bf4e,0x3f393f18,0x3f133edb,0x3f513f67,0xbf7ebf75,0xbdeebe95,0xbe86bedb,0x3f773f67,
0xbf79bf80,0x3e733d7b,0x3dbcbdb0,0x3f7f3f7f,0xbf54bf6a,0x3f103ecf,0x3ede3e89,0x3f673f77,0xbf15bf37,0x3f503f33,0x3f383f16,0x3f323f4f,
0xbf80bf7b,0xbc49be48,0xbde2be95,0x3f7e3f75,0xbf70bf7c,0x3eb23e2f,0x3e823d97,0x3f783f7f,0xbf40bf5c,0x3f2a3f04,0x3f163edb,0x3f4f3f67,
0xbeecbf1d,0x3f633f4a,0x3f573f39,0x3f0c3f31,0xbf7fbf7f,0x3dbcbdc9,0x3d30be16,0x3f803f7d,0xbf64bf76,0x3ee93e8f,0x3ed23e6d,0x3f693f79,
0xbf28bf4a,0x3f413f1d,0x3f383f13,0x3f323f51,0xbeaabf01,0x3f723f5d,0x3f6d3f57,0x3ec13f0c,
};
__device__ __align__(1024) uint8_t g_hT[32 * 262144];
__device__ __align__(1024) bf16 g_U[128 * 2 * 8 * 1024];
__device__ __align__(128) float g_gp[128 * 256];
__device__ __align__(128) uint4 g_agg[16 * 512];
#define CS 32
__device__ __align__(128) unsigned g_cnt[8 * 32];
constexpr int CNT_U = 0, CNT_V = 1, CNT_H = 2  , CNT_DONE = 4, CNT_EPOCH = 5;
#define PROFK(i) do { } while (0)
#define PROFC(i) do { } while (0)
#define PROF(i) do { } while (0)
#define PROFX(i) do { } while (0)
#define PROFR(i) do { } while (0)
#define PROFT(i) do { } while (0)
#define PROFS(i) do { } while (0)
#define PROFG(i) do { } while (0)

constexpr int SLOT = 32768;
constexpr int OFF_HS = 4 * SLOT;
constexpr int OFF_W = OFF_HS + 16384;
constexpr int OFF_F = OFF_W + 2 * 18432;
constexpr int OFF_G = OFF_F + 8192;
constexpr int OFF_K = OFF_G + 1024;
constexpr int OFF_GW = OFF_K + 2048;
constexpr int OFF_U = 6 * SLOT;
constexpr int OFF_BAR = OFF_U + 32768;
constexpr int OFF_SC = OFF_BAR + 320;
constexpr int OFF_KEPT = OFF_SC + 1024;
constexpr int OFF_PROF = OFF_KEPT + 64;
constexpr int SMEM_BYTES = OFF_PROF;
constexpr int BAR_FULL = 0  , BAR_U = 11, BAR_W = 12  , BAR_F = 14  ,
              BAR_EMPTY = 17  , BAR_HW = 22  , BAR_WR = 25, BAR_VW = 26, BAR_S1 = 27,
              BAR_XC = 28  , BAR_HR = 32,
              BAR_CD = 33, BAR_C = 34  , BAR_HD = 36  ;

#define DEVI __device__ __forceinline__
constexpr unsigned SPIN_LIMIT = 1u << 22;

DEVI uint32_t smem_u32(const void* p) { return (uint32_t)__cvta_generic_to_shared(p); }
DEVI uint64_t gtime() { uint64_t t; asm volatile("mov.u64 %0, %%globaltimer;" : "=l"(t)); return t; }
DEVI void mbar_init(uint32_t bar, uint32_t cnt) { asm volatile("mbarrier.init.shared::cta.b64 [%0], %1;" :: "r"(bar), "r"(cnt) : "memory"); }
DEVI void mbar_expect_tx(uint32_t bar, uint32_t bytes) { asm volatile("mbarrier.arrive.expect_tx.shared::cta.b64 _, [%0], %1;" :: "r"(bar), "r"(bytes) : "memory"); }
DEVI void mbar_arrive(uint32_t bar) { asm volatile("mbarrier.arrive.shared::cta.b64 _, [%0];" :: "r"(bar) : "memory"); }
#define WAIT_LOOP "{\n.reg .pred p;\n.reg .u32 n;\nmov.u32 n, 0;\n" \
                  "LW:\nmbarrier.try_wait.parity.shared::cta.b64 p, [%0], %1;\n@p bra LD;\n" \
                  "add.u32 n, n, 1;\nsetp.lt.u32 p, n, 131072;\n@p bra LW;\nLD:\n"
DEVI void mbar_wait(uint32_t bar, uint32_t parity) { asm volatile(WAIT_LOOP "}" :: "r"(bar), "r"(parity) : "memory"); }
DEVI bool elect() {
    uint32_t p;
    asm volatile("{\n.reg .pred P;\nelect.sync _|P, 0xffffffff;\nselp.u32 %0, 1, 0, P;\n}" : "=r"(p));
    return p;
}
DEVI void fence_barrier_init() { asm volatile("fence.mbarrier_init.release.cluster;" ::: "memory"); }
DEVI void fence_proxy_async_smem() { asm volatile("fence.proxy.async.shared::cta;" ::: "memory"); }
DEVI void helper_sync() { asm volatile("bar.sync 1, 128;" ::: "memory"); }

DEVI void pause(unsigned n) {
    asm volatile("{\n.reg .pred p;\n.reg .u32 a, b;\nmov.u32 a, %%clock;\n"
                 "LP:\nmov.u32 b, %%clock;\nsub.u32 b, b, a;\nsetp.lt.u32 p, b, %0;\n@p bra LP;\n}" :: "r"(n) : "memory");
}
DEVI void sched_fence() { asm volatile("{\n.reg .pred p;\n.reg .b32 n;\nLP:\nactivemask.b32 n;\nsetp.eq.u32 p, n, 0;\n@p bra LP;\n}" ::: "memory"); }
#define P_POLL 0
#define NPOLL 1
DEVI void wait_counter(const unsigned* p, unsigned target) {
    unsigned v[NPOLL];
    auto ld = [&](int i) { asm volatile("ld.relaxed.gpu.global.u32 %0, [%1];" : "=r"(v[i]) : "l"(p) : "memory"); };
#pragma unroll
    for (int i = 0; i < NPOLL; i++) { if (i) pause(200); ld(i); }
#pragma unroll 1
    for (unsigned n = 0; n < SPIN_LIMIT; n++) {
#pragma unroll
        for (int i = 0; i < NPOLL; i++) {
            if ((int)(v[i] - target) >= 0) return;
            if (P_POLL) pause(P_POLL);
            ld(i);
        }
    }
}
DEVI void signal_counter(unsigned* p) {
    asm volatile("red.relaxed.gpu.global.add.u32 [%0], 1;" :: "l"(p) : "memory");
}

DEVI void tma_load_3d(uint32_t dst, const CUtensorMap* map, uint32_t bar, int c0, int c1, int c2) {
    asm volatile("cp.async.bulk.tensor.3d.shared::cluster.global.mbarrier::complete_tx::bytes [%0], [%1, {%3, %4, %5}], [%2];"
        :: "r"(dst), "l"(map), "r"(bar), "r"(c0), "r"(c1), "r"(c2) : "memory");
}
DEVI void tma_load_4d(uint32_t dst, const CUtensorMap* map, uint32_t bar, int c0, int c1, int c2, int c3) {
    asm volatile("cp.async.bulk.tensor.4d.shared::cluster.global.mbarrier::complete_tx::bytes [%0], [%1, {%3, %4, %5, %6}], [%2];"
        :: "r"(dst), "l"(map), "r"(bar), "r"(c0), "r"(c1), "r"(c2), "r"(c3) : "memory");
}
DEVI void tma_load_5d(uint32_t dst, const CUtensorMap* map, uint32_t bar, int c0, int c3, int c4) {
    asm volatile("cp.async.bulk.tensor.5d.shared::cluster.global.mbarrier::complete_tx::bytes [%0], [%1, {%3, %6, %6, %4, %5}], [%2];"
        :: "r"(dst), "l"(map), "r"(bar), "r"(c0), "r"(c3), "r"(c4), "r"(0) : "memory");
}
DEVI void tma_store_4d(const CUtensorMap* map, uint32_t src, int c0, int c1, int c2, int c3) {
    asm volatile("cp.async.bulk.tensor.4d.global.shared::cta.bulk_group [%0, {%2, %3, %4, %5}], [%1];"
        :: "l"(map), "r"(src), "r"(c0), "r"(c1), "r"(c2), "r"(c3) : "memory");
}
DEVI void bulk_load(uint32_t dst, const void* src, uint32_t bytes, uint32_t bar) {
    asm volatile("cp.async.bulk.shared::cluster.global.mbarrier::complete_tx::bytes [%0], [%1], %2, [%3];"
        :: "r"(dst), "l"(src), "r"(bytes), "r"(bar) : "memory");
}
DEVI void bulk_prefetch_l2(const void* src, uint32_t bytes) {
    asm volatile("cp.async.bulk.prefetch.L2.global [%0], %1;" :: "l"(src), "r"(bytes) : "memory");
}
DEVI void tma_store_3d(const CUtensorMap* map, uint32_t src, int c0, int c1, int c2) {
    asm volatile("cp.async.bulk.tensor.3d.global.shared::cta.bulk_group [%0, {%2, %3, %4}], [%1];"
        :: "l"(map), "r"(src), "r"(c0), "r"(c1), "r"(c2) : "memory");
}
DEVI void bulk_store(void* dst, uint32_t src, uint32_t bytes) {
    asm volatile("cp.async.bulk.global.shared::cta.bulk_group [%0], [%1], %2;" :: "l"(dst), "r"(src), "r"(bytes) : "memory");
}
DEVI void bulk_commit() { asm volatile("cp.async.bulk.commit_group;" ::: "memory"); }
DEVI void bulk_wait0() { asm volatile("cp.async.bulk.wait_group 0;" ::: "memory"); }

DEVI void wgmma_fence() { asm volatile("wgmma.fence.sync.aligned;" ::: "memory"); }
DEVI void wgmma_commit() { asm volatile("wgmma.commit_group.sync.aligned;" ::: "memory"); }
template<int N> DEVI void wgmma_wait() { asm volatile("wgmma.wait_group.sync.aligned %0;" :: "n"(N) : "memory"); }
template<int N> DEVI void wgmma_wait_all(float (&d)[N]) {
    wgmma_wait<0>();
#pragma unroll
    for (int i = 0; i < N; i++) asm volatile("" : "+f"(d[i]) :: "memory");
}
template<int R> DEVI void reg_alloc() { asm volatile("setmaxnreg.inc.sync.aligned.u32 %0;" :: "n"(R)); }
template<int R> DEVI void reg_dealloc() { asm volatile("setmaxnreg.dec.sync.aligned.u32 %0;" :: "n"(R)); }

DEVI uint64_t make_desc(uint32_t addr, uint32_t lbo, uint32_t sbo, uint32_t mode = 1) {
    return (uint64_t)(((addr & 0x3FFFF) >> 4) | ((lbo >> 4) << 16)) | ((uint64_t)((sbo >> 4) | (mode << 30)) << 32);
}

#define ACC8(a, o) "+f"(a[o+0]), "+f"(a[o+1]), "+f"(a[o+2]), "+f"(a[o+3]), "+f"(a[o+4]), "+f"(a[o+5]), "+f"(a[o+6]), "+f"(a[o+7])
#define OUT8(a, o) "=f"(a[o+0]), "=f"(a[o+1]), "=f"(a[o+2]), "=f"(a[o+3]), "=f"(a[o+4]), "=f"(a[o+5]), "=f"(a[o+6]), "=f"(a[o+7])
#define ACC32(a, o) ACC8(a, o), ACC8(a, o+8), ACC8(a, o+16), ACC8(a, o+24)

template<int TA, int TB>
DEVI void wgmma_n128(float (&d)[64], uint64_t da, uint64_t db, int scale_d) {
    asm volatile("{\n.reg .pred p;\nsetp.ne.b32 p, %66, 0;\n"
        "wgmma.mma_async.sync.aligned.m64n128k16.f32.bf16.bf16 "
        "{%0, %1, %2, %3, %4, %5, %6, %7, %8, %9, %10, %11, %12, %13, %14, %15, "
        "%16, %17, %18, %19, %20, %21, %22, %23, %24, %25, %26, %27, %28, %29, %30, %31, "
        "%32, %33, %34, %35, %36, %37, %38, %39, %40, %41, %42, %43, %44, %45, %46, %47, "
        "%48, %49, %50, %51, %52, %53, %54, %55, %56, %57, %58, %59, %60, %61, %62, %63}, "
        "%64, %65, p, 1, 1, %67, %68;\n}\n"
        : ACC32(d, 0), ACC32(d, 32)
        : "l"(da), "l"(db), "r"(scale_d), "n"(TA), "n"(TB));
}
#define SS_N16 "{\n.reg .pred p;\nsetp.ne.b32 p, 0, 0;\n" \
        "wgmma.mma_async.sync.aligned.m64n16k16.f32.bf16.bf16 " \
        "{%0, %1, %2, %3, %4, %5, %6, %7}, %8, %9, p, 1, 1, %10, 0;\n}\n"
template<int TA> DEVI void wgmma_n16(float* d, uint64_t da, uint64_t db) {
    asm volatile(SS_N16 : OUT8(d, 0) : "l"(da), "l"(db), "n"(TA));
}
#define SS_N8 "{\n.reg .pred p;\nsetp.ne.b32 p, %6, 0;\n" \
        "wgmma.mma_async.sync.aligned.m64n8k16.f32.bf16.bf16 {%0, %1, %2, %3}, %4, %5, p, 1, 1, 0, 0;\n}\n"
DEVI void wgmma_n8(float (&d)[4], uint64_t da, uint64_t db, bool add) {
    if (add) asm volatile(SS_N8 : "+f"(d[0]), "+f"(d[1]), "+f"(d[2]), "+f"(d[3]) : "l"(da), "l"(db), "n"(1));
    else asm volatile(SS_N8 : "=f"(d[0]), "=f"(d[1]), "=f"(d[2]), "=f"(d[3]) : "l"(da), "l"(db), "n"(0));
}
#define RS_N64 "{\n.reg .pred p;\nsetp.ne.b32 p, %37, 0;\n" \
        "wgmma.mma_async.sync.aligned.m64n64k16.f32.bf16.bf16 " \
        "{%0, %1, %2, %3, %4, %5, %6, %7, %8, %9, %10, %11, %12, %13, %14, %15, " \
        "%16, %17, %18, %19, %20, %21, %22, %23, %24, %25, %26, %27, %28, %29, %30, %31}, " \
        "{%32, %33, %34, %35}, %36, p, 1, 1, %38;\n}\n"
template<int SCALE_D, int TB = 0>
DEVI void wgmma_rs_n64(float (&d)[32], const uint32_t (&a)[4], uint64_t db) {
    if (SCALE_D) asm volatile(RS_N64 : ACC32(d, 0) : "r"(a[0]), "r"(a[1]), "r"(a[2]), "r"(a[3]), "l"(db), "n"(1), "n"(TB));
    else asm volatile(RS_N64 : OUT8(d, 0), OUT8(d, 8), OUT8(d, 16), OUT8(d, 24) : "r"(a[0]), "r"(a[1]), "r"(a[2]), "r"(a[3]), "l"(db), "n"(0), "n"(TB));
}
#define SS_N64 "{\n.reg .pred p;\nsetp.ne.b32 p, %34, 0;\n" \
        "wgmma.mma_async.sync.aligned.m64n64k16.f32.bf16.bf16 " \
        "{%0, %1, %2, %3, %4, %5, %6, %7, %8, %9, %10, %11, %12, %13, %14, %15, " \
        "%16, %17, %18, %19, %20, %21, %22, %23, %24, %25, %26, %27, %28, %29, %30, %31}, " \
        "%32, %33, p, 1, 1, 0, 1;\n}\n"
template<int SCALE_D> DEVI void wgmma_ss_n64(float (&d)[32], uint64_t da, uint64_t db) {
    if (SCALE_D) asm volatile(SS_N64 : ACC32(d, 0) : "l"(da), "l"(db), "n"(1));
    else asm volatile(SS_N64 : OUT8(d, 0), OUT8(d, 8), OUT8(d, 16), OUT8(d, 24) : "l"(da), "l"(db), "n"(0));
}
DEVI void ldsm_x4_t(uint32_t (&r)[4], uint32_t addr) {
    asm volatile("ldmatrix.sync.aligned.m8n8.x4.trans.shared.b16 {%0, %1, %2, %3}, [%4];"
        : "=r"(r[0]), "=r"(r[1]), "=r"(r[2]), "=r"(r[3]) : "r"(addr) : "memory");
}
DEVI void ldsm_x4(uint32_t (&r)[4], uint32_t addr) {
    asm volatile("ldmatrix.sync.aligned.m8n8.x4.shared.b16 {%0, %1, %2, %3}, [%4];"
        : "=r"(r[0]), "=r"(r[1]), "=r"(r[2]), "=r"(r[3]) : "r"(addr) : "memory");
}
DEVI void stsm_x4(uint32_t addr, uint32_t r0, uint32_t r1, uint32_t r2, uint32_t r3) {
    asm volatile("stmatrix.sync.aligned.m8n8.x4.shared.b16 [%0], {%1, %2, %3, %4};"
        :: "r"(addr), "r"(r0), "r"(r1), "r"(r2), "r"(r3) : "memory");
}
DEVI void stsm_x4_t(uint32_t addr, uint32_t r0, uint32_t r1, uint32_t r2, uint32_t r3) {
    asm volatile("stmatrix.sync.aligned.m8n8.x4.trans.shared.b16 [%0], {%1, %2, %3, %4};"
        :: "r"(addr), "r"(r0), "r"(r1), "r"(r2), "r"(r3) : "memory");
}
DEVI uint32_t movm(uint32_t a) { uint32_t d; asm volatile("movmatrix.sync.aligned.m8n8.trans.b16 %0, %1;" : "=r"(d) : "r"(a)); return d; }
DEVI uint32_t pack2(float lo, float hi) { uint32_t d; asm("cvt.rn.bf16x2.f32 %0, %1, %2;" : "=r"(d) : "f"(hi), "f"(lo)); return d; }
DEVI float bf_lo(uint32_t v) { return __uint_as_float(v << 16); }
DEVI float bf_hi(uint32_t v) { return __uint_as_float(v & 0xffff0000u); }
DEVI float bf_round(float v) { return __bfloat162float(__float2bfloat16_rn(v)); }
DEVI uint32_t bf_mul2(uint32_t a, uint32_t b) { uint32_t d; asm("mul.rn.bf16x2 %0, %1, %2;" : "=r"(d) : "r"(a), "r"(b)); return d; }
DEVI uint32_t bf_add2(uint32_t a, uint32_t b) { uint32_t d; asm("add.rn.bf16x2 %0, %1, %2;" : "=r"(d) : "r"(a), "r"(b)); return d; }
DEVI uint32_t bf_sub2(uint32_t a, uint32_t b) { uint32_t d; asm("sub.rn.bf16x2 %0, %1, %2;" : "=r"(d) : "r"(a), "r"(b)); return d; }
DEVI uint4 lds128u(uint32_t a) { uint4 v; asm volatile("ld.shared.v4.u32 {%0, %1, %2, %3}, [%4];" : "=r"(v.x), "=r"(v.y), "=r"(v.z), "=r"(v.w) : "r"(a) : "memory"); return v; }
DEVI void sts128u(uint32_t a, uint32_t x, uint32_t y, uint32_t z, uint32_t w) { asm volatile("st.shared.v4.u32 [%0], {%1, %2, %3, %4};" :: "r"(a), "r"(x), "r"(y), "r"(z), "r"(w) : "memory"); }
DEVI uint2 lds64u(uint32_t a) { uint2 v; asm volatile("ld.shared.v2.u32 {%0, %1}, [%2];" : "=r"(v.x), "=r"(v.y) : "r"(a) : "memory"); return v; }
DEVI uint32_t ldg32u(const void* p) { uint32_t v; asm volatile("ld.global.nc.u32 %0, [%1];" : "=r"(v) : "l"(p) : "memory"); return v; }
DEVI void sts64(uint32_t a, float x, float y) { asm volatile("st.shared.v2.f32 [%0], {%1, %2};" :: "r"(a), "f"(x), "f"(y) : "memory"); }
DEVI void sts32(uint32_t a, uint32_t v) { asm volatile("st.shared.u32 [%0], %1;" :: "r"(a), "r"(v) : "memory"); }
DEVI uint32_t lds16(uint32_t a) { uint32_t v; asm volatile("ld.shared.u16 %0, [%1];" : "=r"(v) : "r"(a) : "memory"); return v; }
DEVI void cmul2(uint32_t& x, uint32_t& y, uint32_t c, uint32_t s, uint32_t n) {
    asm("{\n.reg .b32 t, u;\nmul.rn.bf16x2 t, %1, %4;\nmul.rn.bf16x2 u, %1, %2;\n"
        "fma.rn.bf16x2 %1, %0, %3, u;\nfma.rn.bf16x2 %0, %0, %2, t;\n}" : "+r"(x), "+r"(y) : "r"(c), "r"(s), "r"(n));
}
DEVI uint32_t neg2(uint32_t s) { uint32_t n; asm volatile("xor.b32 %0, %1, 0x80008000;" : "=r"(n) : "r"(s)); return n; }
DEVI void cmul2(uint32_t& x, uint32_t& y, uint32_t c, uint32_t s) { cmul2(x, y, c, s, neg2(s)); }
DEVI void cmul2c(uint32_t& x, uint32_t& y, uint32_t c, uint32_t s) { cmul2(x, y, c, neg2(s), s); }
DEVI void sts16(uint32_t a, float v) { asm volatile("st.shared.u16 [%0], %1;" :: "r"(a), "r"(pack2(v, v)) : "memory"); }

DEVI float2 cmul(float2 a, float2 b) { return make_float2(fmaf(a.x, b.x, -a.y * b.y), fmaf(a.x, b.y, a.y * b.x)); }
DEVI float2 cfma(float2 a, float2 b, float2 c) { return make_float2(fmaf(a.x, b.x, fmaf(-a.y, b.y, c.x)), fmaf(a.x, b.y, fmaf(a.y, b.x, c.y))); }

struct Params {
    const bf16 *lam_re, *lam_im, *log_dt, *dskip, *gate_w, *c_re, *c_im, *b_re, *b_im, *x;
    int swapB;
};

#define R8_POLL 8
#define R8B 1
#define SCB 32
#define C0 1
#define R8L 8
DEVI void radix8(uint32_t sb, bool inv, int w, int lane, int bar) {
    const uint64_t dg = make_desc(sb + OFF_G + (inv ? 512 : 0), 128, 256, 0), da = make_desc(sb + OFF_U, 16, 16384);
    float acc[2][64];
#pragma unroll
    for (int i = 0; i < 2; i++) {
        wgmma_fence();
#pragma unroll
        for (int j = 0; j < 8; j++) wgmma_n16<1>(acc[i] + 8 * j, da + 64 * (8 * i + j), dg);
        wgmma_commit();
    }
    const int kk = lane & 7, ch = 2 * w + ((lane >> 3) & 1);
    const uint32_t st = sb + OFF_U + (inv ? (lane >> 4) * 16384 + kk * 128 + ((ch ^ kk) << 4)
        : (kk & 1) * 16384 + (kk >> 2) * 2048 + (lane >> 4) * 1024 + (w >> 1) * 128 + ((((kk & 2) * 2 + ((ch & 3) ^ (kk >> 2) ^ (2 * (kk & 1)))) ^ (w >> 1)) << 4));
    uint32_t sa[4];
#pragma unroll
    for (int i = 0; i < 4; i++) sa[i] = inv ? (st ^ (i << 4)) + i * 1024 : (st ^ (i << 5)) + i * 256;
    uint32_t p[32];
#pragma unroll
    for (int i = 0; i < 2; i++) {
        if (i == 0) wgmma_wait<1>();
#pragma unroll
        for (int j = 0; j < 64; j++) asm volatile("" : "+f"(acc[i][j]) :: "memory");
#pragma unroll
        for (int j = 0; j < 32; j++) p[j] = pack2(acc[i][2 * j], acc[i][2 * j + 1]);
        if (i == 0) {
#pragma unroll
            for (int j = 0; j < 32; j++) asm volatile("" : "+r"(p[j]) :: "memory");
            wgmma_wait<0>();
            asm volatile("bar.sync %0, 128;" :: "r"(bar) : "memory");
        }
#pragma unroll
        for (int j = 0; j < 8; j++) stsm_x4_t(sa[j & 3] + (2 * i + (j >> 2)) * 4096, p[4 * j], p[4 * j + 1], p[4 * j + 2], p[4 * j + 3]);
    }
}

template<int N> DEVI void c_take(float (&acc)[32], uint32_t (&p)[16]) {
    wgmma_wait<N>();
#pragma unroll
    for (int i = 0; i < 32; i++) asm volatile("" : "+f"(acc[i]) :: "memory");
#pragma unroll
    for (int i = 0; i < 16; i++) p[i] = pack2(acc[2 * i], acc[2 * i + 1]);
}
DEVI void c_cols(float (&acc)[32], uint64_t df, uint64_t db) {
    wgmma_fence();
    wgmma_ss_n64<0>(acc, df, db);
#pragma unroll
    for (int s = 1; s < 4; s++) wgmma_ss_n64<1>(acc, df + 2 * s, db + 256 * s);
    wgmma_commit();
}

DEVI void phase_c(uint32_t sb, int ps, bool rot, int w, int lane, const uint4 (&tw)[4]) {
    const int warp = ps, bar = 5 + ps;
    PROFC(0);
    const uint32_t rb = sb + OFF_U + ps * 16384;
    const uint64_t df = make_desc(sb + OFF_F, 16, 1024), db = make_desc(rb, 16, 1024);
    float acc[2][32];
    c_cols(acc[0], df, db);
    c_cols(acc[1], df, db + 128);
    const int g = lane & 7, l3 = (lane >> 3) & 1, l4 = lane >> 4;
    uint32_t wf[2][4][4];
    const uint32_t wo = sb + OFF_W + (1 - ps) * 18432 + l4 * 9216 + g * 64 + ((w ^ (g >> 1)) << 4);
#pragma unroll
    for (int h = 0; h < 2; h++) {
        const uint32_t wm = wo + 4608 + (((rot ? 4 : 3) - 2 * h - l3) & 3) * 1152;
#pragma unroll
        for (int j = 0; j < 4; j++) ldsm_x4_t(wf[h][j], (j < 2 ? wo + (2 * h + l3) * 1152 : wm) + (j & 1) * 512);
    }
    uint32_t tn[8];
#pragma unroll
    for (int j = 0; j < 8; j++) tn[j] = neg2((j & 1) ? tw[j >> 1].w : tw[j >> 1].y);
    auto twiddle = [&](uint32_t& x, uint32_t& y, int j) { cmul2(x, y, (j & 1) ? tw[j >> 1].z : tw[j >> 1].x, (j & 1) ? tw[j >> 1].w : tw[j >> 1].y, tn[j]); };
#pragma unroll
    for (int h = 0; h < 2; h++) {
        uint32_t p[16], a[4][4];
        c_take<1>(acc[h], p);
        if (h == 0) PROFC(1);
#pragma unroll
        for (int i = 0; i < 8; i++) {
            twiddle(p[2 * i], p[2 * i + 1], (i & 3) ^ h);
            a[(i & 3) ^ h][i >> 2] = p[2 * i];
            a[(i & 3) ^ h][2 + (i >> 2)] = p[2 * i + 1];
        }
        wgmma_fence();
        wgmma_rs_n64<0>(acc[h], a[0], df + 4 * ps);
        wgmma_rs_n64<1>(acc[h], a[1], df + 4 * ps + 2);
        wgmma_rs_n64<1>(acc[h], a[2], df + 4 - 4 * ps);
        wgmma_rs_n64<1>(acc[h], a[3], df + 6 - 4 * ps);
        wgmma_commit();
    }
    PROFC(2);
#pragma unroll
    for (int h = 0; h < 2; h++) {
        uint32_t p[16], a[4][4];
        c_take<1>(acc[h], p);
#pragma unroll
        for (int i = 0; i < 8; i++) {
            const int j = i >> 1, r = i & 1;
            if (j < 2) cmul2(p[4 * j + r], p[4 * j + 2 + r], wf[h][j][r], wf[h][j][2 + r]);
            else cmul2c(p[4 * j + r], p[4 * j + 2 + r], wf[h][j][r], wf[h][j][2 + r]);
            a[j][r] = p[4 * j + 2 + r];
            a[j][2 + r] = p[4 * j + r];
        }
        wgmma_fence();
        wgmma_rs_n64<0>(acc[h], a[0], df);
#pragma unroll
        for (int j = 1; j < 4; j++) wgmma_rs_n64<1>(acc[h], a[j], df + 2 * j);
        wgmma_commit();
    }
    PROFC(3);
    const uint32_t xa = rb + w * 4096 + l4 * 1024 + g * 128 + (((4 * l3) ^ g) << 4);
#pragma unroll
    for (int h = 0; h < 2; h++) {
        uint32_t p[16];
        if (h) c_take<0>(acc[1], p); else c_take<1>(acc[0], p);
#pragma unroll
        for (int i = 0; i < 8; i++) twiddle(p[4 * (i >> 1) + (i & 1)], p[4 * (i >> 1) + 2 + (i & 1)], 4 + (i >> 1));
#pragma unroll
        for (int i = 0; i < 16; i++) asm volatile("" : "+r"(p[i]) :: "memory");
        if (h) fence_proxy_async_smem();
        asm volatile("bar.sync %0, 128;" :: "r"(bar) : "memory");
        if (h) c_cols(acc[0], df, db);
#pragma unroll
        for (int j = 0; j < 4; j++) stsm_x4((xa ^ (j << 4)) + h * 2048, p[4 * j], p[4 * j + 1], p[4 * j + 2], p[4 * j + 3]);
    }
    fence_proxy_async_smem();
    asm volatile("bar.sync %0, 128;" :: "r"(bar) : "memory");
    c_cols(acc[1], df, db + 128);
    PROFC(4);
    const uint32_t oa = rb + (4 * w + (g >> 1)) * 1024 + (1 - l3) * 512 + (((4 * (g & 1) + l4) ^ (4 - 4 * l3) ^ (g >> 1)) << 4);
#pragma unroll
    for (int h = 0; h < 2; h++) {
        uint32_t p[16];
        if (h) c_take<0>(acc[1], p);
        else {
            c_take<1>(acc[0], p);
#pragma unroll
            for (int i = 0; i < 16; i++) asm volatile("" : "+r"(p[i]) :: "memory");
            wgmma_wait<0>();
            asm volatile("bar.sync %0, 128;" :: "r"(bar) : "memory");
        }
#pragma unroll
        for (int i = 0; i < 4; i++) {
            const int r = 2 * h + (i >> 1);
            stsm_x4((oa ^ ((r ^ (2 * (i & 1))) << 4)) + r * 128, p[4 * i], p[4 * i + 1], p[4 * i + 2], p[4 * i + 3]);
        }
    }
    PROFC(5);
}

#define P_T 100
#define P_C 300
#define PACE_HA 200
#define PACE_HB 0
#define HN 4
#define PACE_V 100
#define VFIRST 4
#define K_XE 60
#define PACE_H 200
#define T_W0 2000
#define T_XS 2000
#define D_XS 0
#define P_XS 500
#define T_G 0
#define T_BA 1000
#define T_W1 3000
#define P_W 0
#define P_XE 600
#define P_R0 0
#define POL2 0
#define T_B2 4000
#define T_W 5000
#define PACE_U 200
#define PACE_L 0
#define T_FA 0
#define REG_M 216
#define REG_H 72
#define NS 4
#define QJ 2
#define QW 1
#define SLOT_OF(k) (((k) + 1) % 4)
DEVI void tma_prefetch_4d(const CUtensorMap* map, int c0, int c1, int c2, int c3) {
    asm volatile("cp.async.bulk.prefetch.tensor.4d.L2.global [%0, {%1, %2, %3, %4}];" :: "l"(map), "r"(c0), "r"(c1), "r"(c2), "r"(c3) : "memory");
}
DEVI void bar_sync(int id, int n) { asm volatile("bar.sync %0, %1;" :: "r"(id), "r"(n) : "memory"); }
DEVI void bar_arrive(int id, int n) { asm volatile("bar.arrive %0, %1;" :: "r"(id), "r"(n) : "memory"); }
DEVI uint4 ldg128(const void* p) { uint4 v; asm volatile("ld.global.nc.v4.u32 {%0, %1, %2, %3}, [%4];" : "=r"(v.x), "=r"(v.y), "=r"(v.z), "=r"(v.w) : "l"(p)); return v; }
DEVI uint32_t ldg16(const void* p) { uint32_t v; asm volatile("ld.global.nc.u16 %0, [%1];" : "=r"(v) : "l"(p)); return v; }
DEVI uint32_t bf_fma2(uint32_t a, uint32_t b, uint32_t c) { uint32_t d; asm("fma.rn.bf16x2 %0, %1, %2, %3;" : "=r"(d) : "r"(a), "r"(b), "r"(c)); return d; }
DEVI void bulk_wait_read() { asm volatile("cp.async.bulk.wait_group.read 0;" ::: "memory"); }

DEVI float lds32f(uint32_t a) { float v; asm volatile("ld.shared.f32 %0, [%1];" : "=f"(v) : "r"(a) : "memory"); return v; }
DEVI uint32_t mbar_test(uint32_t bar, uint32_t parity) {
    uint32_t ok;
    asm volatile("{\n.reg .pred p;\nmbarrier.test_wait.parity.shared::cta.b64 p, [%1], %2;\nselp.u32 %0, 1, 0, p;\n}" : "=r"(ok) : "r"(bar), "r"(parity) : "memory");
    return ok;
}
template<int TA> DEVI void ring_steps(float (&acc)[2][64], uint32_t sb, uint32_t fb, int n, int ns, int& s, uint32_t& phm, bool first, bool lead, uint32_t rel, int first_bar, int last_bar, int pi) {
    const uint64_t da0 = TA ? make_desc(sb, 2048, 256, 3) : make_desc(sb, 16, 1024), db0 = make_desc(sb + 16384, 16, 1024);
    uint32_t eb = sb + OFF_BAR + 8 * BAR_HR;
    mbar_wait(fb + 8 * s, (phm >> s) & 1);
    if (first_bar) bar_sync(first_bar, 256);
#pragma unroll 1
    for (;;) {
        PROFK(pi++);
        const uint64_t da = da0 + (uint32_t)(s * 2048), db = db0 + (uint32_t)(s * 2048);
        wgmma_fence();
#pragma unroll
        for (int j = 0; j < 4; j++) {
            wgmma_n128<TA, 0>(acc[0], da + (TA ? 32 : 2) * j, db + 2 * j, j || !first);
            wgmma_n128<TA, 0>(acc[1], da + 512 + (TA ? 32 : 2) * j, db + 2 * j, j || !first);
            if (j < 3 && (j + 1) % QJ == 0) {
                wgmma_commit();
                wgmma_wait<QW>();
                if (j + 1 == QJ * QW && lead) mbar_arrive(eb);
                if (j + 1 == QJ * QW) __syncwarp();
                wgmma_fence();
            }
        }
        wgmma_commit();
        first = false;
        phm ^= 1u << s;
        if (--n == 0) break;
        const uint32_t en = rel + 8 * s;
        if (++s == ns) s = 0;
        const uint32_t ok = mbar_test(fb + 8 * s, (phm >> s) & 1);
        wgmma_wait<QW>();
        if (QJ * QW == 4 && lead) mbar_arrive(eb);
        eb = en;
        if (!ok) mbar_wait(fb + 8 * s, (phm >> s) & 1);
        __syncwarp();
    }
    if (last_bar) bar_arrive(last_bar, 256);
    if (QJ * QW == 4) {
        wgmma_wait<QW>();
        if (lead) mbar_arrive(eb);
    }
}

__global__ void __cluster_dims__(2, 1, 1) __launch_bounds__(384, 1)
fused_kernel(const __grid_constant__ CUtensorMap mapB, const __grid_constant__ CUtensorMap mapX,
             const __grid_constant__ CUtensorMap mapXs, const __grid_constant__ CUtensorMap mapU0,
             const __grid_constant__ CUtensorMap mapU2, const __grid_constant__ CUtensorMap mapXe,
             const __grid_constant__ CUtensorMap mapCre, const __grid_constant__ CUtensorMap mapCim,
             const __grid_constant__ CUtensorMap mapV, const __grid_constant__ CUtensorMap mapO,
             const __grid_constant__ CUtensorMap mapWr, const __grid_constant__ CUtensorMap mapWi,
             const __grid_constant__ CUtensorMap mapH,
             const __grid_constant__ Params P) {
    extern __shared__ __align__(1024) uint8_t sm[];
    const uint32_t sb = smem_u32(sm);
    const uint32_t bars = sb + OFF_BAR;
    const unsigned cl = blockIdx.x >> 1;
    const int role = cl < 4 ? 32 + 8 * cl : cl < 36 ? ((cl - 4) & 24) + ((cl - 5) & 7) : cl < 64 ? 33 + (cl - 36) / 7 * 8 + (cl - 30) % 7 : cl;
    const int b = role * 2 + (blockIdx.x & 1), tid = threadIdx.x, warp = __shfl_sync(0xffffffffu, tid >> 5, 0), lane = tid & 31;
    const bool main_cta = b < 128;
    if (b == 129) return;
    const int rp = (b >> 1) & 3, mq = ((b >> 3) & 2) + (b & 1), dt = ((b >> 1) & 4) + (b >> 5), tc = 4 * rp + mq;
    const int cls = b == 128 ? 128 : (b & 31) ? (b & 31) + 64 * (b >> 5) : (b == 64 ? 32 : b == 32 ? 64 : b);
    if (warp != 8 && elect()) {
        if (warp == 11) PROFG(0);
        const int u = warp - (warp > 8);
        asm volatile("prefetch.tensormap [%0];" :: "l"(&mapB + 2 + u) : "memory");
        mbar_init(bars + 8 * (5 + u), 1);
        mbar_init(bars + 8 * (16 + u), u ? 4 : 1);
        mbar_init(bars + 8 * (27 + u), u < 1 ? 4 : u == 6 ? 8 : (u == 7 || u == 8) ? 64 : 1);
        fence_barrier_init();
        fence_proxy_async_smem();
    }
    __syncwarp();
    const bool real_cls = (cls & 127) == 0;
    const int t = tid & 127;
    auto load_epoch = [&]() {
        unsigned e;
        asm volatile("ld.relaxed.gpu.global.u32 %0, [%1];" : "=r"(e) : "l"(&g_cnt[CNT_EPOCH * CS]));
        return e + 1;
    };
    const int g = lane >> 2, q = lane & 3;

    if (warp < 8) {
        reg_alloc<REG_M>();
        const int wg = warp >> 2, w = warp & 3;
        if (tid == 0) PROFX(94);
        bar_sync(0, 384);
        if (tid == 224) PROFG(8);
        auto kept = [&](int i) { uint64_t v; asm volatile("ld.volatile.shared.u64 %0, [%1];" : "=l"(v) : "r"(sb + OFF_KEPT + 8 * i) : "memory"); return v; };
        const uint32_t fb = bars + 8 * (BAR_FULL + 5 * wg);
        uint32_t phm = 0;
        const bool lead = lane == 0;
        const uint32_t rel = bars + 8 * BAR_EMPTY;
        if (wg) {
            {
                const int pp = (dt * 64 + 8 * (t & 64) + (t & 63)) & 1023;
                const uint32_t lr_ = ldg16(P.lam_re + pp), li_ = ldg16(P.lam_im + pp), ld_ = ldg16(P.log_dt + pp);
                const unsigned epoch = load_epoch();
                if (t < 64 && main_cta) g_agg[rp * 2048 + (dt + (t >> 5) * 8) * 128 + lane * 4 + mq] = make_uint4(0u, 0u, 0u, 0u);
                if (t < 4) asm volatile("st.shared.u64 [%0], %1;" :: "r"(sb + OFF_KEPT + 8 * lane),
                    "l"(lane == 0 ? (P.swapB ? 255ull : 127ull) | ((uint64_t)epoch << 32) : lane == 1 ? (uint64_t)g_agg : lane == 2 ? (uint64_t)(c_tab + 10240) : (uint64_t)&mapB) : "memory");
                const float lr = bf_lo(lr_), li = bf_lo(li_);
                const float dl = bf_round(expf(bf_lo(ld_)));
                const float mag = expf(dl * lr);
                float sn, cs; sincospif(dl * li * 0.31830988618379067f, &sn, &cs);
                const float2 l1 = make_float2(mag * cs, mag * sn);
                const float inv = 1.f / (lr * lr + li * li);
                const float2 cf = cmul(make_float2(l1.x - 1.f, l1.y), make_float2(lr * inv, -li * inv));
                sts128u(sb + OFF_K + 16 * t, __float_as_uint(l1.x), __float_as_uint(P.swapB ? -l1.y : l1.y), __float_as_uint(cf.x), __float_as_uint(cf.y));
                if (tid == 128) PROFX(92);
            }
            {
                const int kk = (t >> 3) & 7, r = t & 7;
                float sn, cs;
                sincospif((float)(((cls + 256 * kk) * r) & 2047) * (1.f / 1024.f), &sn, &cs);
                sn *= 1.f / 1024.f; cs *= 1.f / 1024.f;
                const uint32_t gf = sb + OFF_G + kk * 16 + r * 2, gi = sb + OFF_G + 512 + r * 16 + (kk & 1) * 128 + (kk & 6);
                if (t < 64) {
                    sts16(gf, cs); sts16(gf + 128, real_cls ? 0.f : sn); sts16(gf + 256, -sn); sts16(gf + 384, real_cls ? 0.f : cs);
                    sts16(gi, cs); sts16(gi + 8, -sn); sts16(gi + 256, sn); sts16(gi + 264, cs);
                }
            }
            if (main_cta) {
                uint32_t fa[16][4];
                pause(T_FA);
#pragma unroll
                for (int i = 0; i < 16; i++) {
                    asm volatile("ld.global.nc.L1::no_allocate.v4.u32 {%0, %1, %2, %3}, [%4];" : "=r"(fa[i][0]), "=r"(fa[i][1]), "=r"(fa[i][2]), "=r"(fa[i][3]) : "l"((const uint4*)c_tab + i * 128 + t));
                }
                if (t == 0) PROFX(91);
                const uint32_t ua = sb + OFF_U + (lane >> 4) * 4096 + (8 * w + (lane & 7)) * 128 + ((((lane >> 3) & 1) ^ (lane & 7)) << 4);
                float acc[4][32];
                const uint64_t db = make_desc(sb + OFF_U, 8192, 1024);
                uint32_t x[4][8], y[4][8];
                float gp[4][4];
#pragma unroll
                for (int m = 0; m < 6; m++) {
                    if (m >= 2) {
                        const int n = m - 2;
                        if (m < 5) wgmma_wait<1>(); else wgmma_wait<0>();
#pragma unroll
                        for (int i = 0; i < 32; i++) asm volatile("" : "+f"(acc[n][i]) :: "memory");
                        asm volatile("" : "+f"(gp[n][0]), "+f"(gp[n][2]) :: "memory");
#pragma unroll
                        for (int j = 0; j < 8; j++) { x[n][j] = pack2(acc[n][4 * j], acc[n][4 * j + 1]); y[n][j] = pack2(acc[n][4 * j + 2], acc[n][4 * j + 3]); }
                    }
                    if (m < 4) {
                        mbar_wait(bars + 8 * (BAR_XC + m), 0);
                        if (t == 0 && m == 3) PROF(8);
                        wgmma_fence();
                        wgmma_rs_n64<0, 1>(acc[m], fa[4 * m], db + 512 * m);
#pragma unroll
                        for (int j = 1; j < 4; j++) wgmma_rs_n64<1, 1>(acc[m], fa[4 * m + j], db + 512 * m + 128 * j);
#pragma unroll
                        for (int j = 0; j < 4; j++) wgmma_n8(gp[m], make_desc(sb + OFF_U, 16, 1024) + 512 * m + 2 * j, make_desc(sb + OFF_GW, 16, 1024) + 2 * j, j);
                        wgmma_commit();
                    }
                }
                if (t < 4) {
#pragma unroll
                    for (int j = 0; j < 8; j++) {
                        const uint32_t s0 = bf_add2(x[0][j], x[2][j]), s2 = bf_add2(x[1][j], x[3][j]), ty = bf_sub2(y[1][j], y[3][j]), sy = bf_add2(y[1][j], y[3][j]);
                        const uint32_t b0 = y[0][j], b2 = y[2][j];
                        y[1][j] = bf_sub2(x[3][j], x[1][j]); x[1][j] = bf_sub2(x[0][j], x[2][j]);
                        x[0][j] = bf_add2(s0, s2); y[0][j] = bf_sub2(s0, s2);
                        x[2][j] = bf_add2(b0, ty); y[2][j] = bf_add2(sy, b2) ^ 0x80008000u;
                        x[3][j] = bf_sub2(b0, ty); y[3][j] = bf_sub2(b2, sy);
                    }
                } else {
#pragma unroll
                    for (int j = 0; j < 8; j++) {
                        const uint32_t s0x = bf_add2(x[0][j], x[2][j]), s1x = bf_sub2(x[0][j], x[2][j]), s2x = bf_add2(x[1][j], x[3][j]), tx = bf_sub2(x[1][j], x[3][j]);
                        const uint32_t s0y = bf_add2(y[0][j], y[2][j]), s1y = bf_sub2(y[0][j], y[2][j]), s2y = bf_add2(y[1][j], y[3][j]), ty = bf_sub2(y[1][j], y[3][j]);
                        x[0][j] = bf_add2(s0x, s2x); y[0][j] = bf_add2(s0y, s2y);
                        x[1][j] = bf_add2(s1x, ty); y[1][j] = bf_sub2(s1y, tx);
                        x[2][j] = bf_sub2(s0x, s2x); y[2][j] = bf_sub2(s0y, s2y);
                        x[3][j] = bf_sub2(s1x, ty); y[3][j] = bf_add2(s1y, tx);
                    }
                }
                helper_sync();
                if (q == 0) {
#pragma unroll
                    for (int i = 0; i < 2; i++)
                        sts128u(sb + OFF_GW + (16 * w + 8 * i + g) * 16, __float_as_uint(gp[0][2 * i]), __float_as_uint(gp[1][2 * i]), __float_as_uint(gp[2][2 * i]), __float_as_uint(gp[3][2 * i]));
                }
#pragma unroll
                for (int c = 0; c < 4; c++)
#pragma unroll
                    for (int j = 0; j < 8; j += 2) stsm_x4((ua ^ (j << 4)) + c * 8192, x[c][j], x[c][j + 1], y[c][j], y[c][j + 1]);
                if (t == 0) PROF(21);
            }
            fence_proxy_async_smem();
            __syncwarp();
            if (lane == 0) mbar_arrive(bars + 8 * BAR_S1);
        }
        uint4 tw[4];
        auto load_tw = [&]() {
            const uint4* twp = (const uint4*)kept(2) + t;
#pragma unroll
            for (int i = 0; i < 4; i++) tw[i] = ldg128(twp + (i < 2 ? i ^ wg : i & 1) * 128);
        };
        {
            float acc[2][64];
            float2 lam8[2], lam32[2], lam64[2], wq[2], w4[2], l32q[2], ex[2];
            float2 ag[2][4];
            if (main_cta) {
                int sp = wg * SLOT_OF(16);
                ring_steps<0>(acc, sb, fb, 16, 5 - wg, sp, phm, true, lead, rel, 2 * wg, 2 + wg, 16 * wg);
                mbar_wait(bars + 8 * BAR_S1, 0);
                const uint4* ap = (const uint4*)kept(1) + (((tc - 1 - q) >> 2) * 2048 + (dt + 8 * wg) * 128 + t);
                const uint64_t k0 = kept(0);
                const uint32_t fl = (uint32_t)k0, tag = ((uint32_t)(k0 >> 32) & 7) | 8;
                const bool swapB = fl & 128;
                float2 lam1[2], coef[2];
#pragma unroll
                for (int i = 0; i < 2; i++) {
                    const uint4 kv = lds128u(sb + OFF_K + (64 * wg + 32 * i + (t >> 2)) * 16);
                    lam1[i] = make_float2(__uint_as_float(kv.x), __uint_as_float(kv.y));
                    coef[i] = make_float2(__uint_as_float(kv.z), __uint_as_float(kv.w));
                    float2 z = cmul(lam1[i], lam1[i]);
                    z = cmul(z, z);
                    lam8[i] = cmul(z, z);
                    z = cmul(lam8[i], lam8[i]);
                    lam32[i] = cmul(z, z); lam64[i] = cmul(lam32[i], lam32[i]);
                    const float2 l128 = cmul(lam64[i], lam64[i]), l256 = cmul(l128, l128), one = make_float2(1.f, 0.f);
                    w4[i] = cmul(l256, l256);
                    wq[i] = cmul(((tc - 1 - q) & 1) ? l128 : one, ((tc - 1 - q) & 2) ? l256 : one);
                    l32q[i] = cmul((q & 1) ? lam32[i] : one, (q & 2) ? lam64[i] : one);
                    asm volatile("" : "+f"(w4[i].x), "+f"(w4[i].y), "+f"(wq[i].x), "+f"(wq[i].y), "+f"(l32q[i].x), "+f"(l32q[i].y));
                }
                sched_fence();
                wgmma_wait_all(acc[0]);
#pragma unroll
                for (int o = 0; o < 64; o++) asm volatile("" : "+f"(acc[1][o]) :: "memory");
                if (lead) mbar_arrive(rel + 8 * (sp));
                sched_fence();
                if (tid == 0) PROF(3);
                if (tid == 128) PROF(25);
                if (tid == 224) PROFG(12);
                float2 v[2];
#pragma unroll
                for (int c = 0; c < 8; c++) ag[c >> 2][c & 3] = make_float2(acc[c >> 2][16 * (c & 3)], acc[c >> 2][16 * (c & 3) + 2]);
#pragma unroll
                for (int r = 1; r < 8; r++)
#pragma unroll
                    for (int c = 0; c < 8; c++) {
                        const int i = c >> 2, o = 16 * (c & 3) + 4 * (r >> 1) + (r & 1);
                        ag[i][c & 3] = cfma(lam1[i], ag[i][c & 3], make_float2(acc[i][o], acc[i][o + 2]));
                    }
#pragma unroll
                for (int i = 0; i < 2; i++) {
                    v[i] = ag[i][0];
#pragma unroll
                    for (int c = 1; c < 4; c++) v[i] = cfma(lam8[i], v[i], ag[i][c]);
                    float2 n = make_float2(__shfl_up_sync(0xffffffffu, v[i].x, 1, 4), __shfl_up_sync(0xffffffffu, v[i].y, 1, 4));
                    if (q >= 1) v[i] = cfma(lam32[i], n, v[i]);
                    n = make_float2(__shfl_up_sync(0xffffffffu, v[i].x, 2, 4), __shfl_up_sync(0xffffffffu, v[i].y, 2, 4));
                    if (q >= 2) v[i] = cfma(lam64[i], n, v[i]);
                }
                if (q == 3 && tc < 15) {
                    asm volatile("{\n.reg .b64 a, b;\nmov.b64 a, {%1, %2};\nmov.b64 b, {%3, %4};\nst.relaxed.gpu.global.v2.b64 [%0], {a, b};\n}"
                        :: "l"(ap + (2045 + mq)), "r"((__float_as_uint(v[0].x) & ~15u) | tag), "r"(__float_as_uint(v[0].y)),
                           "r"((__float_as_uint(v[1].x) & ~15u) | tag), "r"(__float_as_uint(v[1].y)) : "memory");
                }
                PROFS(72 + 8 * wg);
                sched_fence();
                {
                    float m00[2], m01[2], m10[2], m11[2];
                    auto scale = [&](int i, float& x, float& y) { const float u = fmaf(m00[i], x, m01[i] * y); y = fmaf(m10[i], x, m11[i] * y); x = u; };
#pragma unroll
                    for (int i = 0; i < 2; i++) {
                        ex[i] = make_float2(__shfl_up_sync(0xffffffffu, v[i].x, 1, 4), __shfl_up_sync(0xffffffffu, v[i].y, 1, 4));
                        if (q == 0) ex[i] = make_float2(0.f, 0.f);
                        const float cx = coef[i].x, cy = coef[i].y;
                        m00[i] = cx; m01[i] = -cy; m10[i] = -cy; m11[i] = -cx;
                        if (swapB) { m00[i] = -cy; m01[i] = cx; m10[i] = -cx; m11[i] = -cy; }
                        scale(i, ex[i].x, ex[i].y);
                        scale(i, l32q[i].x, l32q[i].y);
                        if (!swapB) { lam1[i].y = -lam1[i].y; lam8[i].y = -lam8[i].y; }
#pragma unroll
                        for (int o = 0; o < 64; o += 4) {
                            scale(i, acc[i][o], acc[i][o + 2]); scale(i, acc[i][o + 1], acc[i][o + 3]);
                            if ((o + 4) % SCB == 0) {
#pragma unroll
                                for (int u = o + 4 - SCB; u < o + 4; u++) asm volatile("" : "+f"(acc[i][u]));
                                sched_fence();
                            }
                        }
#pragma unroll
                        for (int c = 0; c < 3; c++) scale(i, ag[i][c].x, ag[i][c].y);
                    }
                }
                PROFS(73 + 8 * wg);
                uint4 rr[4];
#pragma unroll
                for (int n = 0; n < 4; n++) rr[n] = make_uint4(tag, 0u, tag, 0u);
                auto poll = [&]() {
#pragma unroll
                    for (int n = 0; n < 4; n++)
                        asm volatile("{\n.reg .b64 a, b;\n.reg .pred p;\nsetp.lt.s32 p, %5, %6;\nmov.b64 a, {%0, %1};\nmov.b64 b, {%2, %3};\n"
                                     "@p ld.relaxed.gpu.global.v2.b64 {a, b}, [%4];\nmov.b64 {%0, %1}, a;\nmov.b64 {%2, %3}, b;\n}"
                            : "+r"(rr[n].x), "+r"(rr[n].y), "+r"(rr[n].z), "+r"(rr[n].w) : "l"(ap - 2048 * n), "r"(4 * n), "r"(tc - q) : "memory");
                };
                poll();
#pragma unroll 1
                for (unsigned n = 0; n < SPIN_LIMIT; n++) {
                    uint32_t bad = 0;
#pragma unroll
                    for (int j = 0; j < 4; j++) bad |= (rr[j].x ^ tag) | (rr[j].z ^ tag);
                    if (!__any_sync(0xffffffffu, bad & 15)) break;
                    if (n < 3) PROFS(74 + 8 * wg + n);
                    poll();
                }
                float2 part[2] = {make_float2(__uint_as_float(rr[3].x), __uint_as_float(rr[3].y)), make_float2(__uint_as_float(rr[3].z), __uint_as_float(rr[3].w))};
#pragma unroll
                for (int n = 2; n >= 0; n--) {
                    part[0] = cfma(w4[0], part[0], make_float2(__uint_as_float(rr[n].x), __uint_as_float(rr[n].y)));
                    part[1] = cfma(w4[1], part[1], make_float2(__uint_as_float(rr[n].z), __uint_as_float(rr[n].w)));
                }
#pragma unroll
                for (int i = 0; i < 2; i++) {
                    part[i] = cmul(wq[i], part[i]);
                    part[i].x += __shfl_xor_sync(0xffffffffu, part[i].x, 1); part[i].y += __shfl_xor_sync(0xffffffffu, part[i].y, 1);
                    part[i].x += __shfl_xor_sync(0xffffffffu, part[i].x, 2); part[i].y += __shfl_xor_sync(0xffffffffu, part[i].y, 2);
                    if (!swapB) part[i].y = -part[i].y;
                    ex[i] = cfma(l32q[i], part[i], ex[i]);
#pragma unroll
                    for (int c = 0; c < 4; c++) { const float2 n = cfma(lam8[i], ex[i], ag[i][c]); ag[i][c] = ex[i]; ex[i] = n; }
                }
                if (t == 0) PROF(4 + 25 * wg);
                const uint32_t hs = sb + OFF_HS + (lane >> 4) * 1024 + w * 256 + (lane & 7) * 32 + (((lane << 1) ^ (lane << 2)) & 16);
#pragma unroll
                for (int i = 0; i < 2; i++) {
                    if (fl & (4 << i)) {
#pragma unroll
                        for (int r = 0; r < 8; r++)
#pragma unroll
                            for (int c = 0; c < 4; c++) {
                                const int o = 16 * c + 4 * (r >> 1) + (r & 1);
                                ag[i][c] = cfma(lam1[i], ag[i][c], make_float2(acc[i][o], acc[i][o + 2]));
                                acc[i][o] = ag[i][c].x; acc[i][o + 2] = ag[i][c].y;
                            }
                    }
                    if (i) {
                        fence_proxy_async_smem();
                        __syncwarp();
                        if (lane == 0) mbar_arrive(bars + 8 * BAR_HW);
                    }
                    mbar_wait(bars + 8 * (wg ? (i ? BAR_WR : BAR_HD) : BAR_EMPTY + 4), 0);
#pragma unroll
                    for (int z = 0; z < 8; z++) {
                        const float* a = &acc[i][2 * z];
                        stsm_x4(hs + i * (16384 + wg * 18432) + (z & 1) * 8192 + (z >> 1) * 2048, pack2(a[0], a[32]), pack2(a[16], a[48]), pack2(a[1], a[33]), pack2(a[17], a[49]));
                    }
                }
                fence_proxy_async_smem();
                __syncwarp();
                if (lane == 0) mbar_arrive(bars + 8 * (BAR_HW + 1));
                load_tw();
                if (t == 0) PROF(5 + 25 * wg);
            } else {
                mbar_wait(bars + 8 * BAR_S1, 0);
                load_tw();
            }
        }
        if (wg) mbar_wait(bars + 8 * BAR_WR, 0);
#pragma unroll 1
        for (int ps = wg; ps < 1 + 2 * wg; ps++) {
            if (ps != 1) {
                mbar_wait(bars + (ps ? 8 * BAR_CD : 8 * BAR_U), 0);
                if (t == 0) PROF(ps ? 7 : 23);
                radix8(sb, ps, w, lane, 5 + wg);
                if (t == 0) PROF(ps ? 24 : 22);
                if (ps) break;
                fence_proxy_async_smem();
                bar_sync(5, 128);
            }
            mbar_wait(bars + 8 * (BAR_C + ps), 0);
            phase_c(sb, ps, b + ps == 0, w, lane, tw);
            fence_proxy_async_smem();
            __syncwarp();
            if (lane == 0) {
                mbar_arrive(bars + 8 * BAR_CD);
                if (!wg) mbar_arrive(bars + 8 * BAR_WR);
            }
        }
        if (wg == 0) {
            if (main_cta) {
                float acc[2][64];
                int s = SLOT_OF(32);
                ring_steps<1>(acc, sb, fb, 31, NS, s, phm, true, lead, rel, 3, 0, 32);
                auto full = [&](int k) { mbar_wait(fb + 8 * SLOT_OF(k), (phm >> SLOT_OF(k)) & 1); PROFT(k); };
                auto hstep = [&](int k, int i) {
                    const uint64_t da = make_desc(sb + SLOT_OF(k) * SLOT + i * 8192, 2048, 256, 3), db = make_desc(sb + SLOT_OF(k) * SLOT + 16384, 16, 1024);
                    wgmma_fence();
#pragma unroll
                    for (int j = 0; j < 4; j++) wgmma_n128<1, 0>(acc[i], da + 32 * j, db + 2 * j, 1);
                };
                auto vstep = [&](int k, int i) {
                    const uint64_t da = make_desc(sb + OFF_U - i * 32768 + k * 8192, 16, 1024), db = make_desc(sb + SLOT_OF(64 + (k >> 1)) * SLOT + (k & 1) * 16384, 8192, 1024);
                    if (k || !i) wgmma_fence();
#pragma unroll
                    for (int j = 0; j < 4; j++) wgmma_n128<0, 1>(acc[i], da + 2 * j, db + 128 * j, 1);
                };
                __syncwarp();
                full(63);
                hstep(63, 0);
                bar_sync(4, 256);
                full(64);
                vstep(0, 0);
                vstep(1, 0);
                const CUtensorMap* maps = (const CUtensorMap*)kept(3);
                const uint32_t ob = sb + OFF_U + w * 2048, oa = ob + g * 256 + (((q >> 1) ^ (2 * g & 6)) << 4) + (q & 1) * 8;
#pragma unroll
                for (int i = 0; i < 2; i++) {
                    uint4 e[8];
                    const uint2 sc = lds64u(sb + OFF_SC + (64 * i + 16 * w + 2 * g) * 4);
                    bar_sync(8 + i, 256);
#pragma unroll
                    for (int j = 0; j < 8; j++) e[j] = lds128u(sb + OFF_HS + i * 16384 + (j >> 2) * 8192 + w * 2048 + (j & 3) * 512 + lane * 16);
                    if (i) wgmma_wait<0>();
                    else {
                        full(65);
                        vstep(2, 0);
                        vstep(3, 0);
                        wgmma_commit();
                        hstep(63, 1);
                        vstep(0, 1);
                        wgmma_commit();
                        wgmma_wait<1>();
                    }
#pragma unroll
                    for (int o = 0; o < 64; o++) asm volatile("" : "+f"(acc[i][o]) :: "memory");
                    if (tid == 0) PROF(17 + i);
                    if (tid == 96 && i) PROFG(20);
#pragma unroll
                    for (int c = 0; c < 4; c++) {
#pragma unroll
                        for (int j = 0; j < 8; j++) {
                            const int o = 16 * c + 2 * j;
                            const uint4 e4 = e[2 * c + (j >> 2)];
                            const uint32_t ev = (j & 2) ? ((j & 1) ? e4.w : e4.z) : ((j & 1) ? e4.y : e4.x);
                            const float f = __uint_as_float((j & 1) ? sc.y : sc.x);
                            sts64((oa ^ ((j >> 1) << 5) ^ ((j & 1) * 144)) + c * 8192 - i * 32768, fmaf(f, acc[i][o], bf_lo(ev)), fmaf(f, acc[i][o + 1], bf_hi(ev)));
                        }
                        if (!i && c >= VFIRST && c < 3) {
                            vstep(c + 1, 1);
                            if (c == 2) wgmma_commit();
                        }
                        fence_proxy_async_smem();
                        __syncwarp();
                        if (elect()) tma_store_3d(maps + 9, ob + c * 8192 - i * 32768, 128 * dt + 32 * c, 128 * (tc & 1) + 64 * i + 16 * w, tc >> 1);
                        __syncwarp();
                        if (!i && c < VFIRST && c < 3) {
                            vstep(c + 1, 1);
                            if (c == 2) wgmma_commit();
                        }
                    }
                }
                if (elect()) {
                    bulk_commit();
                    bulk_wait_read();
                }
                if (tid == 0) PROF(19);
                if (tid == 96) { PROF(20); PROFG(4); }
            }
        } else {
            fence_proxy_async_smem();
            __syncwarp();
            if (lane == 0) mbar_arrive(bars + 8 * BAR_VW);
            __syncwarp();
            if (tid == 224) PROFG(16);
            if (main_cta) {
                float gs[16];
                uint32_t dk[16], tv[4][4];
#pragma unroll
                for (int j = 0; j < 16; j++) gs[j] = __ldcg(g_gp + (16 * (tc >> 1) + j) * 256 + 128 * (tc & 1) + t);
#pragma unroll
                for (int j = 0; j < 16; j++) dk[j] = ldg32u(P.dskip + 128 * dt + 8 * j + 2 * q);
                const int m0 = ((t >> 2) & 14) + (t >> 6), c0 = 4 * ((t ^ (t >> 3)) & 7);
#pragma unroll
                for (int j = 0; j < 16; j++) {
                    const float a = (float)((j & 3) || c0 ? c0 + (j & 3) : -96) * ((float)(128 * (tc & 1) + 4 * (j & 12) + m0) * 0.024543692606170260f);
                    tv[j >> 2][j & 3] = pack2(__cosf(a), -__sinf(a));
                }
#pragma unroll
                for (int j = 0; j < 4; j++) gs[j] = (gs[j] + gs[j + 4]) + (gs[j + 8] + gs[j + 12]);
                gs[0] = (gs[0] + gs[1]) + (gs[2] + gs[3]);
                const float gg = bf_round(__fdividef(1.f, 1.f + __expf(-bf_round(gs[0])))), og = bf_round(1.f - gg), o2 = fmaxf(2.f * og, 0x1p-40f);
                sts32(sb + OFF_SC + 4 * t, __float_as_uint(o2));
                sts32(sb + OFF_SC + 512 + 4 * t, pack2(__fdividef(gg, o2), og));
                bar_sync(6, 128);
                if (t == 0) PROFX(95);
                auto sign = [](uint32_t n) { return (((n + 1) & 2) << 30) | ((n & 2) << 14); };
                const uint32_t sel = (t & 64) ? 0x1032 : 0x3210;
#pragma unroll
                for (int e = 1; e >= 0; e--) {
                    uint32_t f[4];
#pragma unroll
                    for (int j = 0; j < 4; j++) f[j] = lds16(sb + OFF_SC + 512 + (64 * e + 16 * j + m0) * 4) * 0x10001u;
                    mbar_wait(bars + 8 * (e ? BAR_HD + 1 : BAR_U), !e);
#pragma unroll
                    for (int j = 0; j < 16; j++) {
                        const int k = j & 3, r = j >> 2;
                        uint32_t o[4];
#pragma unroll
                        for (int u = 0; u < 4; u++) {
                            uint32_t v = tv[r][u];
                            if (u == 0 && k < 2 && !c0) v = k ? 0x3f80u : 0x3f003f00u | (t & 64) << 25;
                            if (e) v = ((u & 1) ? __byte_perm(v, 0, 0x1032) : v) ^ sign(u);
                            o[u] = bf_mul2((k & 1) ? __byte_perm(v, 0, sel) : v, f[r] ^ sign(k * m0));
                        }
                        sts128u(sb + OFF_U - e * 32768 + (4 * k + r) * 2048 + t * 16, o[0], o[1], o[2], o[3]);
                    }
                }
                fence_proxy_async_smem();
                bar_arrive(4, 256);
                if (t == 0) PROF(16);
                const uint32_t xa = sb + OFF_HS + (16 * w + (lane & 15)) * 128 + (((lane >> 4) ^ (lane & 7)) << 4);
#pragma unroll
                for (int e = 0; e < 2; e++) {
                    const uint2 u = lds64u(sb + OFF_SC + 512 + (64 * e + 16 * w + 2 * g) * 4);
                    const uint32_t o0 = __byte_perm(u.x, 0, 0x3232), o1 = __byte_perm(u.y, 0, 0x3232);
                    uint32_t x[8][4];
                    mbar_wait(bars + 8 * (BAR_W + e), 1);
#pragma unroll
                    for (int j = 0; j < 8; j++) ldsm_x4(x[j], (xa ^ ((j & 3) << 5)) + e * 16384 + (j >> 2) * 8192);
#pragma unroll
                    for (int j = 0; j < 8; j++) {
#pragma unroll
                        for (int c = 0; c < 4; c++) x[j][c] = bf_mul2(bf_mul2(x[j][c], dk[2 * j + (c >> 1)]), (c & 1) ? o1 : o0);
                        sts128u(sb + OFF_HS + e * 16384 + (j >> 2) * 8192 + w * 2048 + (j & 3) * 512 + lane * 16, x[j][0], x[j][1], x[j][2], x[j][3]);
                    }
                    bar_arrive(8 + e, 256);
                    if (t == 0 && !e) PROF(15);
                }
            }
            if (t == 0) {
                const unsigned old = atomicAdd(&g_cnt[CNT_DONE * CS], 1u);
                if (old == 128) { g_cnt[CNT_DONE * CS] = 0; g_cnt[CNT_EPOCH * CS] = (uint32_t)(kept(0) >> 32); }
            }
        }
    } else {
        reg_dealloc<REG_H>();
        const int w = warp - 8;
        if (w == 0) {
            if (elect()) {
                PROF(0);
#pragma unroll
                for (int i = 0; i < 5; i++) mbar_init(bars + 8 * i, 1);
                fence_barrier_init();
                fence_proxy_async_smem();
                PROFX(88);
            }
            __syncwarp();
            bar_arrive(0, 384);
            if (elect()) {
                if (main_cta) {
#pragma unroll 1
                    for (int k = 0; k < 5; k++) {
                        const uint32_t full = bars + 8 * (BAR_FULL + k), st = sb + k * SLOT;
                        mbar_expect_tx(full, SLOT);
                        tma_load_4d(st, &mapB, full, k * 64, 0, 0, dt * 8);
                        tma_load_4d(st + 16384, &mapX, full, k * 64, 0, 0, tc * 64);
                        if (k == 0) PROFX(89);
                        if (P_R0) pause(P_R0);
                    }
                }
                PROF(27);
            }
            __syncwarp();
            bar_sync(7, 64);
            if (main_cta && elect()) {
                int s = 0; uint32_t ph = 0;
#pragma unroll 1
                for (int k = 5; k < 32; k++) {
                    asm volatile(WAIT_LOOP
                        "cp.async.bulk.tensor.4d.shared::cluster.global.mbarrier::complete_tx::bytes [%3], [%5, {%7, %10, %10, %8}], [%2];\n"
                        "cp.async.bulk.tensor.4d.shared::cluster.global.mbarrier::complete_tx::bytes [%4], [%6, {%7, %10, %10, %9}], [%2];\n"
                        "mbarrier.arrive.expect_tx.shared::cta.b64 _, [%2], 32768;\n}"
                        :: "r"(bars + 8 * (BAR_EMPTY + s)), "r"(ph), "r"(bars + 8 * (BAR_FULL + s + (k >> 4) * 5)), "r"(sb + s * SLOT + 16384), "r"(sb + s * SLOT),
                           "l"(&mapX), "l"(&mapB), "r"((k & 15) * 64), "r"(tc * 64), "r"(dt * 8 + (k >> 4) * 64), "r"(0) : "memory");
                    PROFR(k < 19 ? k - 5 : k - 4);
                    if (++s == (k < 15 ? 5 : NS)) { s = 0; ph ^= 1; }
                }
                auto load_x = [&](int e) {
                    mbar_expect_tx(bars + 8 * (BAR_W + e), 16384);
#pragma unroll
                    for (int i = 0; i < 2; i++) tma_load_5d(sb + OFF_HS + e * 16384 + i * 8192, &mapXe, bars + 8 * (BAR_W + e), 128 * dt + 64 * i, 8 * (tc & 1) + 4 * e, tc >> 1);
                };
                const uint8_t* hp = g_hT + tc * 16384;
#pragma unroll 1
                for (int h = 0; h < 32; h++) {
                    if ((h & 15) == 0) mbar_wait(bars + 8 * (BAR_F + (h >> 4)), 0);
                    asm volatile(WAIT_LOOP
                        "cp.async.bulk.tensor.3d.shared::cluster.global.mbarrier::complete_tx::bytes [%3], [%5, {%9, %7, %8}], [%2];\n"
                        "cp.async.bulk.shared::cluster.global.mbarrier::complete_tx::bytes [%4], [%6], 16384, [%2];\n"
                        "mbarrier.arrive.expect_tx.shared::cta.b64 _, [%2], 32768;\n}"
                        :: "r"(bars + 8 * (BAR_EMPTY + s)), "r"(ph), "r"(bars + 8 * (BAR_FULL + s)), "r"(sb + s * SLOT + 16384), "r"(sb + s * SLOT),
                           "l"(&mapCre + (h & 1)), "l"(hp), "r"(dt * 128), "r"(h >> 1), "r"(0) : "memory");
                    PROFR(h + 28);
                    hp += 16 * 16384;
                    if (h == K_XE - 32) load_x(0);
                    if (++s == NS) { s = 0; ph ^= 1; }
                }
                {
                        mbar_wait(bars + 8 * (BAR_F + 2), 0);
#pragma unroll
                        for (int i = 0; i < 2; i++) {
                            const uint32_t pb = bars + 8 * (BAR_XC + i), full = bars + 8 * (BAR_FULL + SLOT_OF(64 + i)), st = sb + SLOT_OF(64 + i) * SLOT;
                            uint32_t rb;
                            asm("mapa.shared::cluster.u32 %0, %1, %2;" : "=r"(rb) : "r"(pb), "r"(~b & 1));
                            asm volatile(WAIT_LOOP "mbarrier.arrive.shared::cluster.b64 _, [%2];\n}" :: "r"(bars + 8 * (BAR_EMPTY + SLOT_OF(64 + i))), "r"(ph), "r"(rb) : "memory");
                            asm volatile(WAIT_LOOP "cp.async.bulk.tensor.3d.shared::cluster.global.mbarrier::complete_tx::bytes.multicast::cluster [%2], [%3, {%5, %6, %7}], [%4], %8;\n}"
                                :: "r"(pb), "r"(1), "r"(st + (b & 1) * 16384), "l"(&mapV), "r"(full), "r"(0), "r"(i * 128 + (b & 1) * 64), "r"((tc >> 1) * 16 + dt * 2), "h"((uint16_t)3) : "memory");
                            mbar_expect_tx(full, SLOT);
                            PROFR(60 + i);
                        }
                    }
                load_x(1);
            }
        } else {
            const unsigned epoch = load_epoch();
            bar_sync(0, 384);
            if (w == 1) {
                bar_arrive(7, 64);
                if (elect()) {
                    if (main_cta) {
                        pause(T_XS);
                        bulk_load(sb + OFF_GW, P.gate_w + (b & 15) * 64, 128, bars + 8 * BAR_XC);
#pragma unroll 1
                        for (int c = 0; c < 4; c++) {
                            mbar_expect_tx(bars + 8 * (BAR_XC + c), c ? 8192 : 8192 + 128);
                            tma_load_4d(sb + OFF_U + c * 8192, &mapXs, bars + 8 * (BAR_XC + c), (b & 15) * 64, 0, c, b >> 4);
                            pause(P_XS);
                        }
                    }
                    mbar_wait(bars + 8 * BAR_S1, 0);
                    if (main_cta) {
#pragma unroll
                        for (int c = 0; c < 4; c++) {
                            if (c) pause(PACE_U);
                            tma_store_4d(&mapU0, sb + OFF_U + c * 8192, (b & 15) * 64, 32 * c, 0, b >> 4);
                        }
                        bulk_store(g_gp + b * 256, sb + OFF_GW, 1024);
                        bulk_commit();
                        bulk_wait0();
                        signal_counter(&g_cnt[CNT_U * CS]);
                    }
                    PROF(9);
                    mbar_expect_tx(bars + 8 * BAR_U, 32768);
                    wait_counter(&g_cnt[CNT_U * CS], epoch * 128);
                    PROF(11);
#pragma unroll
                    for (int i = 0; i < 8; i++) {
                        if (PACE_L && i && !(i & 1)) pause(PACE_L);
                        tma_load_4d(sb + OFF_U + i * 4096, &mapU2, bars + 8 * BAR_U, 0, 0, (i & 3) * 4, b == 128 ? 1 : b == 0 ? 0 : 2 * b + (i >> 2));
                    }
                    if (main_cta) {
#pragma unroll 1
                        for (int i = 0; i < 2; i++) {
#pragma unroll 1
                            for (int j = 0; j < 2 * HN; j++) {
                                const int hf = j / HN, jj = j % HN;
                                if (jj == 0) mbar_wait(bars + 8 * (BAR_HW + hf), i);
                                if (j) pause(i ? PACE_HB : PACE_HA);
                                tma_store_3d(&mapH, sb + OFF_HS + hf * (16384 + i * 18432) + jj * (16384 / HN), 0, 2 * tc + hf, (dt + 8 * i) * 16 + jj * (16 / HN));
                            }
                            bulk_commit();
                            bulk_wait0();
                            signal_counter(&g_cnt[(CNT_H + i) * CS]);
                            mbar_arrive(bars + 8 * (BAR_HD + i));
                            PROF(i ? 6 : 26);
                            wait_counter(&g_cnt[(CNT_H + i) * CS], epoch * 128);
                            mbar_arrive(bars + 8 * (BAR_F + i));
                            PROF(1 + i);
                        }
                    }
                }
            } else {
                const int ld = (1026 * cls) >> 7, lm = (1026 * ((256 - cls) & 255)) >> 7;
                if (elect() && main_cta) {
                    if (w == 3) {
                        pause(T_W);
#pragma unroll 1
                        for (int i = 0; i < 8; i++) {
                            tma_prefetch_4d(&mapWr + (i & 1), 0, (i & 2) ? lm : ld, i >> 2, 0);
                            pause(200);
                        }
                    } else {
                        pause(T_BA + D_XS * tc);
                        if (tc > 4) tma_prefetch_4d(&mapB, tc * 64, 0, 0, dt * 8);
                        pause(T_B2);
                        bulk_prefetch_l2(((b & 1) ? P.b_im : P.b_re) + (64 + (b >> 1)) * 8192, 16384);
                        pause(T_W0 - D_XS * tc);
                    }
                }
#pragma unroll 1
                for (int ps = 0; ps < 2; ps++) {
                    const uint32_t wb = sb + OFF_W + (1 - ps) * 18432;
                    if (w == 2 && elect()) {
                        const uint32_t bw = bars + 8 * (BAR_W + ps);
                        if (ps && main_cta) mbar_wait(bars + 8 * BAR_HD, 0);
                        mbar_expect_tx(bw, ps ? 18432 : 18432 + 8192);
#pragma unroll 1
                        for (int i = 0; i < 4; i++) {
                            tma_load_4d(wb + (i >> 1) * 4608 + (i & 1) * 9216, &mapWr + (i & 1), bw, 0, i < 2 ? ld : lm, (i < 2 || b == 0) ? ps : 1 - ps, 0);
                            pause(P_W);
                        }
                        if (!ps) bulk_load(sb + OFF_F, c_tab + 8192, 8192, bw);
                        PROFX(85 + ps);
                    }
                    if (w == 3 && ps && main_cta && elect()) {
#pragma unroll 1
                        for (int i = 0; i < 8; i++) {
                            bulk_prefetch_l2(((b & 1) ? P.c_im : P.c_re) + (size_t)(b >> 1) * 16384 + i * 2048, 4096);
                            pause(P_C);
                        }
                    }
                    __syncwarp();
                    mbar_wait(bars + 8 * (BAR_W + ps), 0);
                    if (tid == 320) PROF(ps ? 31 : 10);
#pragma unroll 1
                    for (int u = 0; u < 4; u++) {
                        const int row = 2 * (w - 2) + (u >> 1), pl = u & 1;
                        const uint32_t dp = wb + pl * 9216 + row * 1152, mp = wb + pl * 9216 + 4608 + ((b == 0 && ps == 0) ? (4 - row) & 3 : 3 - row) * 1152;
                        const uint32_t od = dp + ((1026 * cls) & 127), om = mp + ((1026 * (256 - cls)) & 127);
                        uint32_t v[4][8], o[4][4];
#pragma unroll
                        for (int i = 0; i < 8; i++) {
                            const uint4 r = lds128u((i < 4 ? (od & ~15u) + 16 * lane + (i >> 1) * 512 : ((om + 1010) & ~15u) - 16 * lane - ((i >> 1) & 1) * 512) + (i & 1) * 16);
                            uint32_t* d = &v[i >> 1][4 * (i & 1)];
                            d[0] = r.x; d[1] = r.y; d[2] = r.z; d[3] = r.w;
                        }
                        const uint32_t e0 = lds16(om), e1 = lds16(od + 1024);
                        auto fwd = [&](int ws) {
#pragma unroll
                            for (int k = 0; k < 8; k++) o[k >> 2][k & 3] = __byte_perm(v[k >> 2][ws + (k & 3)], v[k >> 2][ws + (k & 3) + 1], (cls & 1) ? 0x5432 : 0x3210);
                        };
                        auto mir = [&](int ws) {
#pragma unroll
                            for (int k = 8; k < 16; k++) o[k >> 2][k & 3] = __byte_perm(v[k >> 2][ws + 3 - (k & 3)], v[k >> 2][ws + 4 - (k & 3)], (cls & 1) ? 0x1032 : 0x3254);
                        };
                        switch ((cls >> 1) & 3) { case 0: fwd(0); break; case 1: fwd(1); break; case 2: fwd(2); break; default: fwd(3); }
                        switch (((1 - cls) >> 1) & 3) { case 0: mir(0); break; case 1: mir(1); break; case 2: mir(2); break; default: mir(3); }
                        if (lane == 0) {
                            o[0][0] = pack2(fmaf(pl ? -0.5f : 0.5f, bf_lo(e0), 0.5f * bf_lo(o[0][0])), bf_hi(o[0][0]));
                            o[2][0] = pack2(fmaf(pl ? -0.5f : 0.5f, bf_lo(e1), 0.5f * bf_lo(o[2][0])), bf_hi(o[2][0]));
                        }
                        __syncwarp();
#pragma unroll
                        for (int i = 0; i < 4; i++)
                            sts128u((i < 2 ? dp : mp) + (i & 1) * 512 + ((lane * 16) ^ ((lane << 1) & 48)), o[i][0], o[i][1], o[i][2], o[i][3]);
                    }
                    if (ps) fence_proxy_async_smem();
                    mbar_arrive(bars + 8 * (BAR_C + ps));
                    if (tid == 320) PROF(ps ? 12 : 28);
                }
                if (w == 2 && elect()) {
                    {
                        mbar_wait(bars + 8 * BAR_VW, 0);
#pragma unroll 1
                        for (int i = 0; i < (real_cls ? 4 : 8); i++) {
                            if (i) pause(PACE_V);
                            tma_store_4d(&mapU2, sb + OFF_U + i * 4096, 0, 0, (i & 3) * 4, b == 128 ? 1 : 2 * b + (i >> 2));
                        }
                        bulk_commit();
                        bulk_wait_read();
                        mbar_arrive(bars + 8 * BAR_U);
                        bulk_wait0();
                        signal_counter(&g_cnt[CNT_V * CS]);
                        PROF(13);
                        if (main_cta) {
                            wait_counter(&g_cnt[CNT_V * CS], epoch * 129);
                            mbar_arrive(bars + 8 * (BAR_F + 2));
                            PROF(14);
                        }
                    }
                }
            }
        }
    }
}

typedef CUresult (*PFN_encodeTiled)(CUtensorMap*, CUtensorMapDataType, cuuint32_t, void*, const cuuint64_t*, const cuuint64_t*,
                                    const cuuint32_t*, const cuuint32_t*, CUtensorMapInterleave, CUtensorMapSwizzle,
                                    CUtensorMapL2promotion, CUtensorMapFloatOOBfill);

static CUtensorMap make_map(PFN_encodeTiled enc, const void* ptr, int rank, const cuuint64_t* dims, const cuuint64_t* strides, const cuuint32_t* box,
                            CUtensorMapSwizzle sw = CU_TENSOR_MAP_SWIZZLE_128B, CUtensorMapDataType dt = CU_TENSOR_MAP_DATA_TYPE_BFLOAT16) {
    CUtensorMap m;
    cuuint32_t es[5] = {1, 1, 1, 1, 1};
    enc(&m, dt, rank, (void*)ptr, dims, strides, box, es, CU_TENSOR_MAP_INTERLEAVE_NONE,
        sw, CU_TENSOR_MAP_L2_PROMOTION_L2_128B, CU_TENSOR_MAP_FLOAT_OOB_FILL_NONE);
    return m;
}

extern "C" void kernel_launch(void* const* d_in, const int* in_sizes, int n_in, void* d_out, int out_size) {
    const bf16* x = (const bf16*)d_in[0];
    const bf16* wr = (const bf16*)d_in[1];
    const bf16* wi = (const bf16*)d_in[2];
    const bf16* Bre = (const bf16*)d_in[6];
    const bf16* Bim = (const bf16*)d_in[7];
    const bf16* Cre = (const bf16*)d_in[8];
    const bf16* Cim = (const bf16*)d_in[9];

    void* fn = nullptr;
    cudaDriverEntryPointQueryResult st;
    cudaGetDriverEntryPoint("cuTensorMapEncodeTiled", &fn, cudaEnableDefault, &st);
    PFN_encodeTiled enc = (PFN_encodeTiled)fn;
    void *p_hT, *p_U;
    cudaGetSymbolAddress(&p_hT, g_hT);
    cudaGetSymbolAddress(&p_U, g_U);

    Params P;
    P.lam_re = (const bf16*)d_in[4]; P.lam_im = (const bf16*)d_in[5]; P.log_dt = (const bf16*)d_in[10];
    P.dskip = (const bf16*)d_in[11]; P.gate_w = (const bf16*)d_in[12]; P.c_re = Cre; P.c_im = Cim; P.b_re = Bre; P.b_im = Bim; P.x = x;
    P.swapB = Bim < Bre;

    CUtensorMap mB, mX, mCre, mCim, mXs, mU0, mV, mU2, mXe, mO, mWr, mWi, mH;
    {
        cuuint64_t d[4] = {64, 2052, 2, 4}, s[3] = {128, 262656, 525312};
        cuuint32_t bx[4] = {64, 9, 1, 4};
        mWr = make_map(enc, wr, 4, d, s, bx, CU_TENSOR_MAP_SWIZZLE_NONE);
        mWi = make_map(enc, wi, 4, d, s, bx, CU_TENSOR_MAP_SWIZZLE_NONE);
    }
    {
        cuuint64_t d[3] = {128, 32, 256}, s[2] = {1024, 32768};
        cuuint32_t bx[3] = {128, 1, 16 / HN};
        mH = make_map(enc, p_hT, 3, d, s, bx, CU_TENSOR_MAP_SWIZZLE_NONE, CU_TENSOR_MAP_DATA_TYPE_UINT64);
    }
    {
        const bf16* lo = P.swapB ? Bim : Bre; const bf16* hi = P.swapB ? Bre : Bim;
        cuuint64_t d[4] = {1024, 8, 2, 128}, s[3] = {2048, (cuuint64_t)((const char*)hi - (const char*)lo), 16384};
        cuuint32_t bx[4] = {64, 8, 2, 8};
        mB = make_map(enc, lo, 4, d, s, bx);
    }
    {
        cuuint64_t d[4] = {1024, 2, 4, 976}, s[3] = {2048, 32 * 2048, 2 * 2048};
        cuuint32_t bx[4] = {64, 2, 4, 16};
        mX = make_map(enc, x, 4, d, s, bx);
    }
    {
        cuuint64_t d[3] = {64, 1024, 16}, s[2] = {2048, 128};
        cuuint32_t bx[3] = {64, 128, 1};
        mCre = make_map(enc, Cre, 3, d, s, bx);
        mCim = make_map(enc, Cim, 3, d, s, bx);
    }
    {
        cuuint64_t d[3] = {64, 256, 128}, s[2] = {16384, 128};
        cuuint32_t bx[3] = {64, 64, 2};
        mV = make_map(enc, p_U, 3, d, s, bx);
    }
    {
        cuuint64_t d[5] = {1024, 8, 2, 16, 8}, s[4] = {16 * 2048, 8 * 2048, 128 * 2048, 2048};
        cuuint32_t bx[5] = {64, 8, 2, 4, 1};
        mXe = make_map(enc, x, 5, d, s, bx);
    }
    {
        cuuint64_t d[3] = {1024, 256, 8}, s[2] = {8 * 4096, 4096};
        cuuint32_t bx[3] = {32, 16, 1};
        mO = make_map(enc, d_out, 3, d, s, bx, CU_TENSOR_MAP_SWIZZLE_128B, CU_TENSOR_MAP_DATA_TYPE_FLOAT32);
    }
    {
        cuuint64_t d[4] = {1024, 64, 4, 8}, s[3] = {32 * 2048, 8 * 2048, 2048};
        cuuint32_t bx[4] = {64, 64, 1, 1};
        mXs = make_map(enc, x, 4, d, s, bx);
    }
    {
        cuuint64_t d[4] = {1024, 128, 2, 8}, s[3] = {32768, 16384, 2048};
        cuuint32_t bx[4] = {64, 32, 2, 1};
        mU0 = make_map(enc, p_U, 4, d, s, bx);
    }
    {
        cuuint64_t d[4] = {64, 8, 16, 256}, s[3] = {2048, 128, 16384};
        cuuint32_t bx[4] = {64, 8, 4, 1};
        mU2 = make_map(enc, p_U, 4, d, s, bx);
    }
    cudaFuncSetAttribute(fused_kernel, cudaFuncAttributeMaxDynamicSharedMemorySize, SMEM_BYTES);
    fused_kernel<<<130, 384, SMEM_BYTES, cudaStreamPerThread>>>(mB, mX, mXs, mU0, mU2, mXe, mCre, mCim, mV, mO, mWr, mWi, mH, P);
}
```

```cpp
#include <cuda_runtime.h>
#include <cuda_bf16.h>
#include <cuda.h>
#include <stdint.h>

typedef __nv_bfloat16 bf16;

__device__ const __align__(128) uint32_t c_tab[10240] = {
0x3f803f80,0xbf803f80,0x3f803f80,0xbf803f80,0x3f803f80,0xbf803f80,0x3f803f80,0xbf803f80,0x3f803f80,0xbf803f80,0x3f803f80,0xbf803f80,
0x3f803f80,0xbf803f80,0x3f803f80,0xbf803f80,0x3f7f3f80,0xbdc98000,0x3f223f35,0xbf46bf35,0x3f753f7b,0xbe95be48,0x3ef13f0e,0xbf62bf55,
0x3f623f6d,0xbef1bec4,0x3e953ec4,0xbf75bf6d,0x3f463f55,0xbf22bf0e,0x3dc93e48,0xbf7fbf7b,0x3f7b3f80,0xbe488000,0xbe480000,0xbf7bbf80,
0x3f553f6d,0xbf0ebec4,0xbf0ebec4,0xbf55bf6d,0x3f0e3f35,0xbf55bf35,0xbf55bf35,0xbf0ebf35,0x3e483ec4,0xbf7bbf6d,0xbf7bbf6d,0xbe48bec4,
0x3f753f80,0xbe958000,0xbf62bf35,0xbef1bf35,0x3f223f55,0xbf46bf0e,0xbf7fbf7b,0x3dc9be48,0x3dc93ec4,0xbf7fbf6d,0xbf46bf6d,0x3f223ec4,
0xbef1be48,0xbf62bf7b,0xbe95bf0e,0x3f753f55,0x3f6d3f80,0xbec48000,0xbf6dbf80,0x3ec48000,0x3ec43f35,0xbf6dbf35,0xbec4bf35,0x3f6d3f35,
0xbec40000,0xbf6dbf80,0x3ec40000,0x3f6d3f80,0xbf6dbf35,0xbec4bf35,0x3f6d3f35,0x3ec43f35,0x3f623f80,0xbef18000,0xbe95bf35,0x3f753f35,
0x3dc93f0e,0xbf7fbf55,0x3f223e48,0x3f463f7b,0xbf46bec4,0xbf22bf6d,0x3f7f3f6d,0xbdc93ec4,0xbf75bf7b,0x3e95be48,0x3ef13f55,0xbf62bf0e,
0x3f553f80,0xbf0e8000,0x3f0e0000,0x3f553f80,0xbe483ec4,0xbf7bbf6d,0x3f7b3f6d,0xbe483ec4,0xbf7bbf35,0xbe48bf35,0x3e483f35,0xbf7bbf35,
0xbf0ebf6d,0x3f553ec4,0xbf55bec4,0xbf0ebf6d,0x3f463f80,0xbf228000,0x3f7f3f35,0x3dc93f35,0xbef13e48,0xbf62bf7b,0x3e953f55,0xbf75bf0e,
0xbf75bf6d,0x3e95bec4,0xbf62bec4,0xbef1bf6d,0x3dc9bf0e,0x3f7f3f55,0xbf22bf7b,0x3f463e48,0x3f353f80,0xbf358000,0x3f353f80,0xbf358000,
0xbf350000,0xbf35bf80,0xbf350000,0xbf35bf80,0xbf35bf80,0x3f358000,0xbf35bf80,0x3f358000,0x3f350000,0x3f353f80,0x3f350000,0x3f353f80,
0x3f223f80,0xbf468000,0xbdc93f35,0xbf7fbf35,0xbf62be48,0xbef1bf7b,0xbf75bf55,0x3e95bf0e,0xbe95bf6d,0x3f753ec4,0x3ef1bec4,0x3f623f6d,
0x3f7f3f0e,0x3dc93f55,0x3f463f7b,0xbf223e48,0x3f0e3f80,0xbf558000,0xbf550000,0xbf0ebf80,0xbf7bbec4,0xbe48bf6d,0xbe48bf6d,0x3f7b3ec4,
0x3e48bf35,0x3f7b3f35,0x3f7b3f35,0xbe483f35,0x3f553f6d,0xbf0e3ec4,0xbf0e3ec4,0xbf55bf6d,0x3ef13f80,0xbf628000,0xbf75bf35,0x3e95bf35,
0xbf7fbf0e,0x3dc9bf55,0x3f46be48,0x3f223f7b,0x3f22bec4,0x3f463f6d,0x3dc93f6d,0xbf7fbec4,0x3e953f7b,0xbf75be48,0xbf62bf55,0x3ef1bf0e,
0x3ec43f80,0xbf6d8000,0xbec4bf80,0x3f6d8000,0xbf6dbf35,0x3ec4bf35,0x3f6d3f35,0xbec43f35,0x3f6d0000,0x3ec43f80,0xbf6d0000,0xbec4bf80,
0xbec43f35,0xbf6dbf35,0x3ec4bf35,0x3f6d3f35,0x3e953f80,0xbf758000,0x3ef1bf35,0x3f623f35,0xbf46bf55,0x3f22bf0e,0x3dc93f7b,0xbf7fbe48,
0x3f7f3ec4,0xbdc93f6d,0xbf22bf6d,0x3f46bec4,0xbf623e48,0xbef1bf7b,0x3f753f0e,0xbe953f55,0x3e483f80,0xbf7b8000,0x3f7b0000,0x3e483f80,
0xbf0ebf6d,0x3f55bec4,0xbf553ec4,0xbf0ebf6d,0x3f553f35,0xbf0e3f35,0x3f0ebf35,0x3f553f35,0xbf7bbec4,0x3e48bf6d,0xbe483f6d,0xbf7bbec4,
0x3dc93f80,0xbf7f8000,0x3f463f35,0xbf223f35,0xbe95bf7b,0x3f75be48,0xbf62bf0e,0x3ef1bf55,0x3ef13f6d,0xbf623ec4,0x3f753ec4,0xbe953f6d,
0xbf22bf55,0x3f46bf0e,0xbf7fbe48,0x3dc9bf7b,0x3f80,0xbf808000,0x3f80,0xbf808000,0xbf80,0x3f808000,0xbf80,0x3f808000,
0x3f80,0xbf808000,0x3f80,0xbf808000,0xbf80,0x3f808000,0xbf80,0x3f808000,0xbdc93f80,0xbf7f8000,0xbf463f35,0xbf22bf35,
0x3e95bf7b,0x3f753e48,0x3f62bf0e,0x3ef13f55,0xbef13f6d,0xbf62bec4,0xbf753ec4,0xbe95bf6d,0x3f22bf55,0x3f463f0e,0x3f7fbe48,0x3dc93f7b,
0xbe483f80,0xbf7b8000,0xbf7b0000,0x3e48bf80,0x3f0ebf6d,0x3f553ec4,0x3f553ec4,0xbf0e3f6d,0xbf553f35,0xbf0ebf35,0xbf0ebf35,0x3f55bf35,
0x3f7bbec4,0x3e483f6d,0x3e483f6d,0xbf7b3ec4,0xbe953f80,0xbf758000,0xbef1bf35,0x3f62bf35,0x3f46bf55,0x3f223f0e,0xbdc93f7b,0xbf7f3e48,
0xbf7f3ec4,0xbdc9bf6d,0x3f22bf6d,0x3f463ec4,0x3f623e48,0xbef13f7b,0xbf753f0e,0xbe95bf55,0xbec43f80,0xbf6d8000,0x3ec4bf80,0x3f6d8000,
0x3f6dbf35,0x3ec43f35,0xbf6d3f35,0xbec4bf35,0xbf6d0000,0x3ec4bf80,0x3f6d0000,0xbec43f80,0x3ec43f35,0xbf6d3f35,0xbec4bf35,0x3f6dbf35,
0xbef13f80,0xbf628000,0x3f75bf35,0x3e953f35,0x3f7fbf0e,0x3dc93f55,0xbf46be48,0x3f22bf7b,0xbf22bec4,0x3f46bf6d,0xbdc93f6d,0xbf7f3ec4,
0xbe953f7b,0xbf753e48,0x3f62bf55,0x3ef13f0e,0xbf0e3f80,0xbf558000,0x3f550000,0xbf0e3f80,0x3f7bbec4,0xbe483f6d,0x3e48bf6d,0x3f7bbec4,
0xbe48bf35,0x3f7bbf35,0xbf7b3f35,0xbe48bf35,0xbf553f6d,0xbf0ebec4,0x3f0e3ec4,0xbf553f6d,0xbf223f80,0xbf468000,0x3dc93f35,0xbf7f3f35,
0x3f62be48,0xbef13f7b,0x3f75bf55,0x3e953f0e,0x3e95bf6d,0x3f75bec4,0xbef1bec4,0x3f62bf6d,0xbf7f3f0e,0x3dc9bf55,0xbf463f7b,0xbf22be48,
0xbf353f80,0xbf358000,0xbf353f80,0xbf358000,0x3f350000,0xbf353f80,0x3f350000,0xbf353f80,0x3f35bf80,0x3f358000,0x3f35bf80,0x3f358000,
0xbf350000,0x3f35bf80,0xbf350000,0x3f35bf80,0xbf463f80,0xbf228000,0xbf7f3f35,0x3dc9bf35,0x3ef13e48,0xbf623f7b,0xbe953f55,0xbf753f0e,
0x3f75bf6d,0x3e953ec4,0x3f62bec4,0xbef13f6d,0xbdc9bf0e,0x3f7fbf55,0x3f22bf7b,0x3f46be48,0xbf553f80,0xbf0e8000,0xbf0e0000,0x3f55bf80,
0x3e483ec4,0xbf7b3f6d,0xbf7b3f6d,0xbe48bec4,0x3f7bbf35,0xbe483f35,0xbe483f35,0xbf7b3f35,0x3f0ebf6d,0x3f55bec4,0x3f55bec4,0xbf0e3f6d,
0xbf623f80,0xbef18000,0x3e95bf35,0x3f75bf35,0xbdc93f0e,0xbf7f3f55,0xbf223e48,0x3f46bf7b,0x3f46bec4,0xbf223f6d,0xbf7f3f6d,0xbdc9bec4,
0x3f75bf7b,0x3e953e48,0xbef13f55,0xbf623f0e,0xbf6d3f80,0xbec48000,0x3f6dbf80,0x3ec48000,0xbec43f35,0xbf6d3f35,0x3ec4bf35,0x3f6dbf35,
0x3ec40000,0xbf6d3f80,0xbec40000,0x3f6dbf80,0x3f6dbf35,0xbec43f35,0xbf6d3f35,0x3ec4bf35,0xbf753f80,0xbe958000,0x3f62bf35,0xbef13f35,
0xbf223f55,0xbf463f0e,0x3f7fbf7b,0x3dc93e48,0xbdc93ec4,0xbf7f3f6d,0x3f46bf6d,0x3f22bec4,0x3ef1be48,0xbf623f7b,0x3e95bf0e,0x3f75bf55,
0xbf7b3f80,0xbe488000,0x3e480000,0xbf7b3f80,0xbf553f6d,0xbf0e3ec4,0x3f0ebec4,0xbf553f6d,0xbf0e3f35,0xbf553f35,0x3f55bf35,0xbf0e3f35,
0xbe483ec4,0xbf7b3f6d,0x3f7bbf6d,0xbe483ec4,0xbf7f3f80,0xbdc98000,0xbf223f35,0xbf463f35,0xbf753f7b,0xbe953e48,0xbef13f0e,0xbf623f55,
0xbf623f6d,0xbef13ec4,0xbe953ec4,0xbf753f6d,0xbf463f55,0xbf223f0e,0xbdc93e48,0xbf7f3f7b,0x3f803f80,0xbf803f80,0x3f803f80,0xbf803f80,
0x3f803f80,0xbf803f80,0x3f803f80,0xbf803f80,0x3f803f80,0xbf803f80,0x3f803f80,0xbf803f80,0x3f803f80,0xbf803f80,0x3f803f80,0xbf803f80,
0xbdc90000,0xbf7fbf80,0xbf46bf35,0xbf22bf35,0xbe95be48,0xbf75bf7b,0xbf62bf55,0xbef1bf0e,0xbef1bec4,0xbf62bf6d,0xbf75bf6d,0xbe95bec4,
0xbf22bf0e,0xbf46bf55,0xbf7fbf7b,0xbdc9be48,0xbf7bbf80,0x3e488000,0x3e480000,0x3f7b3f80,0xbf55bf6d,0x3f0e3ec4,0x3f0e3ec4,0x3f553f6d,
0xbf0ebf35,0x3f553f35,0x3f553f35,0x3f0e3f35,0xbe48bec4,0x3f7b3f6d,0x3f7b3f6d,0x3e483ec4,0x3e950000,0x3f753f80,0x3ef13f35,0xbf62bf35,
0x3f463f0e,0x3f223f55,0xbdc93e48,0xbf7fbf7b,0x3f7f3f6d,0x3dc93ec4,0xbf22bec4,0xbf46bf6d,0x3f623f7b,0xbef1be48,0xbf75bf55,0xbe95bf0e,
0x3f6d3f80,0xbec48000,0xbf6dbf80,0x3ec48000,0x3ec43f35,0xbf6dbf35,0xbec4bf35,0x3f6d3f35,0xbec40000,0xbf6dbf80,0x3ec40000,0x3f6d3f80,
0xbf6dbf35,0xbec4bf35,0x3f6d3f35,0x3ec43f35,0xbef10000,0xbf62bf80,0x3f753f35,0x3e953f35,0xbf7fbf55,0xbdc9bf0e,0x3f463f7b,0xbf22be48,
0xbf22bf6d,0x3f463ec4,0xbdc93ec4,0xbf7fbf6d,0x3e95be48,0x3f753f7b,0xbf62bf0e,0xbef1bf55,0xbf55bf80,0x3f0e8000,0xbf0e0000,0xbf55bf80,
0x3e48bec4,0x3f7b3f6d,0xbf7bbf6d,0x3e48bec4,0x3f7b3f35,0x3e483f35,0xbe48bf35,0x3f7b3f35,0x3f0e3f6d,0xbf55bec4,0x3f553ec4,0x3f0e3f6d,
0x3f220000,0x3f463f80,0xbdc9bf35,0x3f7f3f35,0x3f623f7b,0xbef13e48,0x3f753f0e,0x3e953f55,0xbe953ec4,0xbf75bf6d,0x3ef13f6d,0xbf62bec4,
0xbf7fbf55,0x3dc9bf0e,0xbf46be48,0xbf22bf7b,0x3f353f80,0xbf358000,0x3f353f80,0xbf358000,0xbf350000,0xbf35bf80,0xbf350000,0xbf35bf80,
0xbf35bf80,0x3f358000,0xbf35bf80,0x3f358000,0x3f350000,0x3f353f80,0x3f350000,0x3f353f80,0xbf460000,0xbf22bf80,0xbf7fbf35,0x3dc9bf35,
0xbef1bf7b,0x3f623e48,0x3e95bf0e,0x3f753f55,0x3f753ec4,0x3e953f6d,0x3f623f6d,0xbef13ec4,0x3dc93f55,0xbf7fbf0e,0xbf223e48,0xbf46bf7b,
0xbf0ebf80,0x3f558000,0x3f550000,0x3f0e3f80,0x3f7b3ec4,0x3e483f6d,0x3e483f6d,0xbf7bbec4,0xbe483f35,0xbf7bbf35,0xbf7bbf35,0x3e48bf35,
0xbf55bf6d,0x3f0ebec4,0x3f0ebec4,0x3f553f6d,0x3f620000,0x3ef13f80,0xbe953f35,0xbf75bf35,0xbdc93f55,0xbf7fbf0e,0xbf22bf7b,0x3f46be48,
0xbf46bf6d,0x3f22bec4,0x3f7f3ec4,0x3dc93f6d,0x3f753e48,0x3e953f7b,0xbef13f0e,0xbf62bf55,0x3ec43f80,0xbf6d8000,0xbec4bf80,0x3f6d8000,
0xbf6dbf35,0x3ec4bf35,0x3f6d3f35,0xbec43f35,0x3f6d0000,0x3ec43f80,0xbf6d0000,0xbec4bf80,0xbec43f35,0xbf6dbf35,0x3ec4bf35,0x3f6d3f35,
0xbf750000,0xbe95bf80,0x3f623f35,0xbef13f35,0x3f22bf0e,0x3f463f55,0xbf7fbe48,0xbdc9bf7b,0xbdc93f6d,0xbf7fbec4,0x3f46bec4,0x3f223f6d,
0xbef1bf7b,0x3f62be48,0xbe953f55,0xbf75bf0e,0xbe48bf80,0x3f7b8000,0xbf7b0000,0xbe48bf80,0x3f0e3f6d,0xbf553ec4,0x3f55bec4,0x3f0e3f6d,
0xbf55bf35,0x3f0ebf35,0xbf0e3f35,0xbf55bf35,0x3f7b3ec4,0xbe483f6d,0x3e48bf6d,0x3f7b3ec4,0x3f7f0000,0x3dc93f80,0x3f22bf35,0x3f463f35,
0xbf753e48,0xbe95bf7b,0xbef13f55,0xbf62bf0e,0x3f62bec4,0x3ef13f6d,0x3e95bf6d,0x3f753ec4,0xbf463f0e,0xbf22bf55,0xbdc93f7b,0xbf7fbe48,
0x3f80,0xbf808000,0x3f80,0xbf808000,0xbf80,0x3f808000,0xbf80,0x3f808000,0x3f80,0xbf808000,0x3f80,0xbf808000,
0xbf80,0x3f808000,0xbf80,0x3f808000,0xbf7f0000,0x3dc9bf80,0xbf22bf35,0x3f46bf35,0x3f753e48,0xbe953f7b,0x3ef13f55,0xbf623f0e,
0xbf62bec4,0x3ef1bf6d,0xbe95bf6d,0x3f75bec4,0x3f463f0e,0xbf223f55,0x3dc93f7b,0xbf7f3e48,0x3e48bf80,0x3f7b8000,0x3f7b0000,0xbe483f80,
0xbf0e3f6d,0xbf55bec4,0xbf55bec4,0x3f0ebf6d,0x3f55bf35,0x3f0e3f35,0x3f0e3f35,0xbf553f35,0xbf7b3ec4,0xbe48bf6d,0xbe48bf6d,0x3f7bbec4,
0x3f750000,0xbe953f80,0xbf623f35,0xbef1bf35,0xbf22bf0e,0x3f46bf55,0x3f7fbe48,0xbdc93f7b,0x3dc93f6d,0xbf7f3ec4,0xbf46bec4,0x3f22bf6d,
0x3ef1bf7b,0x3f623e48,0x3e953f55,0xbf753f0e,0xbec43f80,0xbf6d8000,0x3ec4bf80,0x3f6d8000,0x3f6dbf35,0x3ec43f35,0xbf6d3f35,0xbec4bf35,
0xbf6d0000,0x3ec4bf80,0x3f6d0000,0xbec43f80,0x3ec43f35,0xbf6d3f35,0xbec4bf35,0x3f6dbf35,0xbf620000,0x3ef1bf80,0x3e953f35,0xbf753f35,
0x3dc93f55,0xbf7f3f0e,0x3f22bf7b,0x3f463e48,0x3f46bf6d,0x3f223ec4,0xbf7f3ec4,0x3dc9bf6d,0xbf753e48,0x3e95bf7b,0x3ef13f0e,0xbf623f55,
0x3f0ebf80,0x3f558000,0xbf550000,0x3f0ebf80,0xbf7b3ec4,0x3e48bf6d,0xbe483f6d,0xbf7b3ec4,0x3e483f35,0xbf7b3f35,0x3f7bbf35,0x3e483f35,
0x3f55bf6d,0x3f0e3ec4,0xbf0ebec4,0x3f55bf6d,0x3f460000,0xbf223f80,0x3f7fbf35,0x3dc93f35,0x3ef1bf7b,0x3f62be48,0xbe95bf0e,0x3f75bf55,
0xbf753ec4,0x3e95bf6d,0xbf623f6d,0xbef1bec4,0xbdc93f55,0xbf7f3f0e,0x3f223e48,0xbf463f7b,0xbf353f80,0xbf358000,0xbf353f80,0xbf358000,
0x3f350000,0xbf353f80,0x3f350000,0xbf353f80,0x3f35bf80,0x3f358000,0x3f35bf80,0x3f358000,0xbf350000,0x3f35bf80,0xbf350000,0x3f35bf80,
0xbf220000,0x3f46bf80,0x3dc9bf35,0x3f7fbf35,0xbf623f7b,0xbef1be48,0xbf753f0e,0x3e95bf55,0x3e953ec4,0xbf753f6d,0xbef13f6d,0xbf623ec4,
0x3f7fbf55,0x3dc93f0e,0x3f46be48,0xbf223f7b,0x3f55bf80,0x3f0e8000,0x3f0e0000,0xbf553f80,0xbe48bec4,0x3f7bbf6d,0x3f7bbf6d,0x3e483ec4,
0xbf7b3f35,0x3e48bf35,0x3e48bf35,0x3f7bbf35,0xbf0e3f6d,0xbf553ec4,0xbf553ec4,0x3f0ebf6d,0x3ef10000,0xbf623f80,0xbf753f35,0x3e95bf35,
0x3f7fbf55,0xbdc93f0e,0xbf463f7b,0xbf223e48,0x3f22bf6d,0x3f46bec4,0x3dc93ec4,0xbf7f3f6d,0xbe95be48,0x3f75bf7b,0x3f62bf0e,0xbef13f55,
0xbf6d3f80,0xbec48000,0x3f6dbf80,0x3ec48000,0xbec43f35,0xbf6d3f35,0x3ec4bf35,0x3f6dbf35,0x3ec40000,0xbf6d3f80,0xbec40000,0x3f6dbf80,
0x3f6dbf35,0xbec43f35,0xbf6d3f35,0x3ec4bf35,0xbe950000,0x3f75bf80,0xbef13f35,0xbf623f35,0xbf463f0e,0x3f22bf55,0x3dc93e48,0xbf7f3f7b,
0xbf7f3f6d,0x3dc9bec4,0x3f22bec4,0xbf463f6d,0xbf623f7b,0xbef13e48,0x3f75bf55,0xbe953f0e,0x3f7bbf80,0x3e488000,0xbe480000,0x3f7bbf80,
0x3f55bf6d,0x3f0ebec4,0xbf0e3ec4,0x3f55bf6d,0x3f0ebf35,0x3f55bf35,0xbf553f35,0x3f0ebf35,0x3e48bec4,0x3f7bbf6d,0xbf7b3f6d,0x3e48bec4,
0x3dc90000,0xbf7f3f80,0x3f46bf35,0xbf223f35,0x3e95be48,0xbf753f7b,0x3f62bf55,0xbef13f0e,0x3ef1bec4,0xbf623f6d,0x3f75bf6d,0xbe953ec4,
0x3f22bf0e,0xbf463f55,0x3f7fbf7b,0xbdc93e48,0x3f803f80,0xbf803f80,0x3f803f80,0xbf803f80,0x3f803f80,0xbf803f80,0x3f803f80,0xbf803f80,
0x3f803f80,0xbf803f80,0x3f803f80,0xbf803f80,0x3f803f80,0xbf803f80,0x3f803f80,0xbf803f80,0xbf7fbf80,0x3dc98000,0xbf22bf35,0x3f463f35,
0xbf75bf7b,0x3e953e48,0xbef1bf0e,0x3f623f55,0xbf62bf6d,0x3ef13ec4,0xbe95bec4,0x3f753f6d,0xbf46bf55,0x3f223f0e,0xbdc9be48,0x3f7f3f7b,
0x3f7b3f80,0xbe488000,0xbe480000,0xbf7bbf80,0x3f553f6d,0xbf0ebec4,0xbf0ebec4,0xbf55bf6d,0x3f0e3f35,0xbf55bf35,0xbf55bf35,0xbf0ebf35,
0x3e483ec4,0xbf7bbf6d,0xbf7bbf6d,0xbe48bec4,0xbf75bf80,0x3e958000,0x3f623f35,0x3ef13f35,0xbf22bf55,0x3f463f0e,0x3f7f3f7b,0xbdc93e48,
0xbdc9bec4,0x3f7f3f6d,0x3f463f6d,0xbf22bec4,0x3ef13e48,0x3f623f7b,0x3e953f0e,0xbf75bf55,0x3f6d3f80,0xbec48000,0xbf6dbf80,0x3ec48000,
0x3ec43f35,0xbf6dbf35,0xbec4bf35,0x3f6d3f35,0xbec40000,0xbf6dbf80,0x3ec40000,0x3f6d3f80,0xbf6dbf35,0xbec4bf35,0x3f6d3f35,0x3ec43f35,
0xbf62bf80,0x3ef18000,0x3e953f35,0xbf75bf35,0xbdc9bf0e,0x3f7f3f55,0xbf22be48,0xbf46bf7b,0x3f463ec4,0x3f223f6d,0xbf7fbf6d,0x3dc9bec4,
0x3f753f7b,0xbe953e48,0xbef1bf55,0x3f623f0e,0x3f553f80,0xbf0e8000,0x3f0e0000,0x3f553f80,0xbe483ec4,0xbf7bbf6d,0x3f7b3f6d,0xbe483ec4,
0xbf7bbf35,0xbe48bf35,0x3e483f35,0xbf7bbf35,0xbf0ebf6d,0x3f553ec4,0xbf55bec4,0xbf0ebf6d,0xbf46bf80,0x3f228000,0xbf7fbf35,0xbdc9bf35,
0x3ef1be48,0x3f623f7b,0xbe95bf55,0x3f753f0e,0x3f753f6d,0xbe953ec4,0x3f623ec4,0x3ef13f6d,0xbdc93f0e,0xbf7fbf55,0x3f223f7b,0xbf46be48,
0x3f353f80,0xbf358000,0x3f353f80,0xbf358000,0xbf350000,0xbf35bf80,0xbf350000,0xbf35bf80,0xbf35bf80,0x3f358000,0xbf35bf80,0x3f358000,
0x3f350000,0x3f353f80,0x3f350000,0x3f353f80,0xbf22bf80,0x3f468000,0x3dc9bf35,0x3f7f3f35,0x3f623e48,0x3ef13f7b,0x3f753f55,0xbe953f0e,
0x3e953f6d,0xbf75bec4,0xbef13ec4,0xbf62bf6d,0xbf7fbf0e,0xbdc9bf55,0xbf46bf7b,0x3f22be48,0x3f0e3f80,0xbf558000,0xbf550000,0xbf0ebf80,
0xbf7bbec4,0xbe48bf6d,0xbe48bf6d,0x3f7b3ec4,0x3e48bf35,0x3f7b3f35,0x3f7b3f35,0xbe483f35,0x3f553f6d,0xbf0e3ec4,0xbf0e3ec4,0xbf55bf6d,
0xbef1bf80,0x3f628000,0x3f753f35,0xbe953f35,0x3f7f3f0e,0xbdc93f55,0xbf463e48,0xbf22bf7b,0xbf223ec4,0xbf46bf6d,0xbdc9bf6d,0x3f7f3ec4,
0xbe95bf7b,0x3f753e48,0x3f623f55,0xbef13f0e,0x3ec43f80,0xbf6d8000,0xbec4bf80,0x3f6d8000,0xbf6dbf35,0x3ec4bf35,0x3f6d3f35,0xbec43f35,
0x3f6d0000,0x3ec43f80,0xbf6d0000,0xbec4bf80,0xbec43f35,0xbf6dbf35,0x3ec4bf35,0x3f6d3f35,0xbe95bf80,0x3f758000,0xbef13f35,0xbf62bf35,
0x3f463f55,0xbf223f0e,0xbdc9bf7b,0x3f7f3e48,0xbf7fbec4,0x3dc9bf6d,0x3f223f6d,0xbf463ec4,0x3f62be48,0x3ef13f7b,0xbf75bf0e,0x3e95bf55,
0x3e483f80,0xbf7b8000,0x3f7b0000,0x3e483f80,0xbf0ebf6d,0x3f55bec4,0xbf553ec4,0xbf0ebf6d,0x3f553f35,0xbf0e3f35,0x3f0ebf35,0x3f553f35,
0xbf7bbec4,0x3e48bf6d,0xbe483f6d,0xbf7bbec4,0xbdc9bf80,0x3f7f8000,0xbf46bf35,0x3f22bf35,0x3e953f7b,0xbf753e48,0x3f623f0e,0xbef13f55,
0xbef1bf6d,0x3f62bec4,0xbf75bec4,0x3e95bf6d,0x3f223f55,0xbf463f0e,0x3f7f3e48,0xbdc93f7b,0x3f80,0xbf808000,0x3f80,0xbf808000,
0xbf80,0x3f808000,0xbf80,0x3f808000,0x3f80,0xbf808000,0x3f80,0xbf808000,0xbf80,0x3f808000,0xbf80,0x3f808000,
0x3dc9bf80,0x3f7f8000,0x3f46bf35,0x3f223f35,0xbe953f7b,0xbf75be48,0xbf623f0e,0xbef1bf55,0x3ef1bf6d,0x3f623ec4,0x3f75bec4,0x3e953f6d,
0xbf223f55,0xbf46bf0e,0xbf7f3e48,0xbdc9bf7b,0xbe483f80,0xbf7b8000,0xbf7b0000,0x3e48bf80,0x3f0ebf6d,0x3f553ec4,0x3f553ec4,0xbf0e3f6d,
0xbf553f35,0xbf0ebf35,0xbf0ebf35,0x3f55bf35,0x3f7bbec4,0x3e483f6d,0x3e483f6d,0xbf7b3ec4,0x3e95bf80,0x3f758000,0x3ef13f35,0xbf623f35,
0xbf463f55,0xbf22bf0e,0x3dc9bf7b,0x3f7fbe48,0x3f7fbec4,0x3dc93f6d,0xbf223f6d,0xbf46bec4,0xbf62be48,0x3ef1bf7b,0x3f75bf0e,0x3e953f55,
0xbec43f80,0xbf6d8000,0x3ec4bf80,0x3f6d8000,0x3f6dbf35,0x3ec43f35,0xbf6d3f35,0xbec4bf35,0xbf6d0000,0x3ec4bf80,0x3f6d0000,0xbec43f80,
0x3ec43f35,0xbf6d3f35,0xbec4bf35,0x3f6dbf35,0x3ef1bf80,0x3f628000,0xbf753f35,0xbe95bf35,0xbf7f3f0e,0xbdc9bf55,0x3f463e48,0xbf223f7b,
0x3f223ec4,0xbf463f6d,0x3dc9bf6d,0x3f7fbec4,0x3e95bf7b,0x3f75be48,0xbf623f55,0xbef1bf0e,0xbf0e3f80,0xbf558000,0x3f550000,0xbf0e3f80,
0x3f7bbec4,0xbe483f6d,0x3e48bf6d,0x3f7bbec4,0xbe48bf35,0x3f7bbf35,0xbf7b3f35,0xbe48bf35,0xbf553f6d,0xbf0ebec4,0x3f0e3ec4,0xbf553f6d,
0x3f22bf80,0x3f468000,0xbdc9bf35,0x3f7fbf35,0xbf623e48,0x3ef1bf7b,0xbf753f55,0xbe95bf0e,0xbe953f6d,0xbf753ec4,0x3ef13ec4,0xbf623f6d,
0x3f7fbf0e,0xbdc93f55,0x3f46bf7b,0x3f223e48,0xbf353f80,0xbf358000,0xbf353f80,0xbf358000,0x3f350000,0xbf353f80,0x3f350000,0xbf353f80,
0x3f35bf80,0x3f358000,0x3f35bf80,0x3f358000,0xbf350000,0x3f35bf80,0xbf350000,0x3f35bf80,0x3f46bf80,0x3f228000,0x3f7fbf35,0xbdc93f35,
0xbef1be48,0x3f62bf7b,0x3e95bf55,0x3f75bf0e,0xbf753f6d,0xbe95bec4,0xbf623ec4,0x3ef1bf6d,0x3dc93f0e,0xbf7f3f55,0xbf223f7b,0xbf463e48,
0xbf553f80,0xbf0e8000,0xbf0e0000,0x3f55bf80,0x3e483ec4,0xbf7b3f6d,0xbf7b3f6d,0xbe48bec4,0x3f7bbf35,0xbe483f35,0xbe483f35,0xbf7b3f35,
0x3f0ebf6d,0x3f55bec4,0x3f55bec4,0xbf0e3f6d,0x3f62bf80,0x3ef18000,0xbe953f35,0xbf753f35,0x3dc9bf0e,0x3f7fbf55,0x3f22be48,0xbf463f7b,
0xbf463ec4,0x3f22bf6d,0x3f7fbf6d,0x3dc93ec4,0xbf753f7b,0xbe95be48,0x3ef1bf55,0x3f62bf0e,0xbf6d3f80,0xbec48000,0x3f6dbf80,0x3ec48000,
0xbec43f35,0xbf6d3f35,0x3ec4bf35,0x3f6dbf35,0x3ec40000,0xbf6d3f80,0xbec40000,0x3f6dbf80,0x3f6dbf35,0xbec43f35,0xbf6d3f35,0x3ec4bf35,
0x3f75bf80,0x3e958000,0xbf623f35,0x3ef1bf35,0x3f22bf55,0x3f46bf0e,0xbf7f3f7b,0xbdc9be48,0x3dc9bec4,0x3f7fbf6d,0xbf463f6d,0xbf223ec4,
0xbef13e48,0x3f62bf7b,0xbe953f0e,0xbf753f55,0xbf7b3f80,0xbe488000,0x3e480000,0xbf7b3f80,0xbf553f6d,0xbf0e3ec4,0x3f0ebec4,0xbf553f6d,
0xbf0e3f35,0xbf553f35,0x3f55bf35,0xbf0e3f35,0xbe483ec4,0xbf7b3f6d,0x3f7bbf6d,0xbe483ec4,0x3f7fbf80,0x3dc98000,0x3f22bf35,0x3f46bf35,
0x3f75bf7b,0x3e95be48,0x3ef1bf0e,0x3f62bf55,0x3f62bf6d,0x3ef1bec4,0x3e95bec4,0x3f75bf6d,0x3f46bf55,0x3f22bf0e,0x3dc9be48,0x3f7fbf7b,
0x3f803f80,0xbf803f80,0x3f803f80,0xbf803f80,0x3f803f80,0xbf803f80,0x3f803f80,0xbf803f80,0x3f803f80,0xbf803f80,0x3f803f80,0xbf803f80,
0x3f803f80,0xbf803f80,0x3f803f80,0xbf803f80,0x3dc90000,0x3f7f3f80,0x3f463f35,0x3f223f35,0x3e953e48,0x3f753f7b,0x3f623f55,0x3ef13f0e,
0x3ef13ec4,0x3f623f6d,0x3f753f6d,0x3e953ec4,0x3f223f0e,0x3f463f55,0x3f7f3f7b,0x3dc93e48,0xbf7bbf80,0x3e488000,0x3e480000,0x3f7b3f80,
0xbf55bf6d,0x3f0e3ec4,0x3f0e3ec4,0x3f553f6d,0xbf0ebf35,0x3f553f35,0x3f553f35,0x3f0e3f35,0xbe48bec4,0x3f7b3f6d,0x3f7b3f6d,0x3e483ec4,
0xbe950000,0xbf75bf80,0xbef1bf35,0x3f623f35,0xbf46bf0e,0xbf22bf55,0x3dc9be48,0x3f7f3f7b,0xbf7fbf6d,0xbdc9bec4,0x3f223ec4,0x3f463f6d,
0xbf62bf7b,0x3ef13e48,0x3f753f55,0x3e953f0e,0x3f6d3f80,0xbec48000,0xbf6dbf80,0x3ec48000,0x3ec43f35,0xbf6dbf35,0xbec4bf35,0x3f6d3f35,
0xbec40000,0xbf6dbf80,0x3ec40000,0x3f6d3f80,0xbf6dbf35,0xbec4bf35,0x3f6d3f35,0x3ec43f35,0x3ef10000,0x3f623f80,0xbf75bf35,0xbe95bf35,
0x3f7f3f55,0x3dc93f0e,0xbf46bf7b,0x3f223e48,0x3f223f6d,0xbf46bec4,0x3dc9bec4,0x3f7f3f6d,0xbe953e48,0xbf75bf7b,0x3f623f0e,0x3ef13f55,
0xbf55bf80,0x3f0e8000,0xbf0e0000,0xbf55bf80,0x3e48bec4,0x3f7b3f6d,0xbf7bbf6d,0x3e48bec4,0x3f7b3f35,0x3e483f35,0xbe48bf35,0x3f7b3f35,
0x3f0e3f6d,0xbf55bec4,0x3f553ec4,0x3f0e3f6d,0xbf220000,0xbf46bf80,0x3dc93f35,0xbf7fbf35,0xbf62bf7b,0x3ef1be48,0xbf75bf0e,0xbe95bf55,
0x3e95bec4,0x3f753f6d,0xbef1bf6d,0x3f623ec4,0x3f7f3f55,0xbdc93f0e,0x3f463e48,0x3f223f7b,0x3f353f80,0xbf358000,0x3f353f80,0xbf358000,
0xbf350000,0xbf35bf80,0xbf350000,0xbf35bf80,0xbf35bf80,0x3f358000,0xbf35bf80,0x3f358000,0x3f350000,0x3f353f80,0x3f350000,0x3f353f80,
0x3f460000,0x3f223f80,0x3f7f3f35,0xbdc93f35,0x3ef13f7b,0xbf62be48,0xbe953f0e,0xbf75bf55,0xbf75bec4,0xbe95bf6d,0xbf62bf6d,0x3ef1bec4,
0xbdc9bf55,0x3f7f3f0e,0x3f22be48,0x3f463f7b,0xbf0ebf80,0x3f558000,0x3f550000,0x3f0e3f80,0x3f7b3ec4,0x3e483f6d,0x3e483f6d,0xbf7bbec4,
0xbe483f35,0xbf7bbf35,0xbf7bbf35,0x3e48bf35,0xbf55bf6d,0x3f0ebec4,0x3f0ebec4,0x3f553f6d,0xbf620000,0xbef1bf80,0x3e95bf35,0x3f753f35,
0x3dc9bf55,0x3f7f3f0e,0x3f223f7b,0xbf463e48,0x3f463f6d,0xbf223ec4,0xbf7fbec4,0xbdc9bf6d,0xbf75be48,0xbe95bf7b,0x3ef1bf0e,0x3f623f55,
0x3ec43f80,0xbf6d8000,0xbec4bf80,0x3f6d8000,0xbf6dbf35,0x3ec4bf35,0x3f6d3f35,0xbec43f35,0x3f6d0000,0x3ec43f80,0xbf6d0000,0xbec4bf80,
0xbec43f35,0xbf6dbf35,0x3ec4bf35,0x3f6d3f35,0x3f750000,0x3e953f80,0xbf62bf35,0x3ef1bf35,0xbf223f0e,0xbf46bf55,0x3f7f3e48,0x3dc93f7b,
0x3dc9bf6d,0x3f7f3ec4,0xbf463ec4,0xbf22bf6d,0x3ef13f7b,0xbf623e48,0x3e95bf55,0x3f753f0e,0xbe48bf80,0x3f7b8000,0xbf7b0000,0xbe48bf80,
0x3f0e3f6d,0xbf553ec4,0x3f55bec4,0x3f0e3f6d,0xbf55bf35,0x3f0ebf35,0xbf0e3f35,0xbf55bf35,0x3f7b3ec4,0xbe483f6d,0x3e48bf6d,0x3f7b3ec4,
0xbf7f0000,0xbdc9bf80,0xbf223f35,0xbf46bf35,0x3f75be48,0x3e953f7b,0x3ef1bf55,0x3f623f0e,0xbf623ec4,0xbef1bf6d,0xbe953f6d,0xbf75bec4,
0x3f46bf0e,0x3f223f55,0x3dc9bf7b,0x3f7f3e48,0x3f80,0xbf808000,0x3f80,0xbf808000,0xbf80,0x3f808000,0xbf80,0x3f808000,
0x3f80,0xbf808000,0x3f80,0xbf808000,0xbf80,0x3f808000,0xbf80,0x3f808000,0x3f7f0000,0xbdc93f80,0x3f223f35,0xbf463f35,
0xbf75be48,0x3e95bf7b,0xbef1bf55,0x3f62bf0e,0x3f623ec4,0xbef13f6d,0x3e953f6d,0xbf753ec4,0xbf46bf0e,0x3f22bf55,0xbdc9bf7b,0x3f7fbe48,
0x3e48bf80,0x3f7b8000,0x3f7b0000,0xbe483f80,0xbf0e3f6d,0xbf55bec4,0xbf55bec4,0x3f0ebf6d,0x3f55bf35,0x3f0e3f35,0x3f0e3f35,0xbf553f35,
0xbf7b3ec4,0xbe48bf6d,0xbe48bf6d,0x3f7bbec4,0xbf750000,0x3e95bf80,0x3f62bf35,0x3ef13f35,0x3f223f0e,0xbf463f55,0xbf7f3e48,0x3dc9bf7b,
0xbdc9bf6d,0x3f7fbec4,0x3f463ec4,0xbf223f6d,0xbef13f7b,0xbf62be48,0xbe95bf55,0x3f75bf0e,0xbec43f80,0xbf6d8000,0x3ec4bf80,0x3f6d8000,
0x3f6dbf35,0x3ec43f35,0xbf6d3f35,0xbec4bf35,0xbf6d0000,0x3ec4bf80,0x3f6d0000,0xbec43f80,0x3ec43f35,0xbf6d3f35,0xbec4bf35,0x3f6dbf35,
0x3f620000,0xbef13f80,0xbe95bf35,0x3f75bf35,0xbdc9bf55,0x3f7fbf0e,0xbf223f7b,0xbf46be48,0xbf463f6d,0xbf22bec4,0x3f7fbec4,0xbdc93f6d,
0x3f75be48,0xbe953f7b,0xbef1bf0e,0x3f62bf55,0x3f0ebf80,0x3f558000,0xbf550000,0x3f0ebf80,0xbf7b3ec4,0x3e48bf6d,0xbe483f6d,0xbf7b3ec4,
0x3e483f35,0xbf7b3f35,0x3f7bbf35,0x3e483f35,0x3f55bf6d,0x3f0e3ec4,0xbf0ebec4,0x3f55bf6d,0xbf460000,0x3f22bf80,0xbf7f3f35,0xbdc9bf35,
0xbef13f7b,0xbf623e48,0x3e953f0e,0xbf753f55,0x3f75bec4,0xbe953f6d,0x3f62bf6d,0x3ef13ec4,0x3dc9bf55,0x3f7fbf0e,0xbf22be48,0x3f46bf7b,
0xbf353f80,0xbf358000,0xbf353f80,0xbf358000,0x3f350000,0xbf353f80,0x3f350000,0xbf353f80,0x3f35bf80,0x3f358000,0x3f35bf80,0x3f358000,
0xbf350000,0x3f35bf80,0xbf350000,0x3f35bf80,0x3f220000,0xbf463f80,0xbdc93f35,0xbf7f3f35,0x3f62bf7b,0x3ef13e48,0x3f75bf0e,0xbe953f55,
0xbe95bec4,0x3f75bf6d,0x3ef1bf6d,0x3f62bec4,0xbf7f3f55,0xbdc9bf0e,0xbf463e48,0x3f22bf7b,0x3f55bf80,0x3f0e8000,0x3f0e0000,0xbf553f80,
0xbe48bec4,0x3f7bbf6d,0x3f7bbf6d,0x3e483ec4,0xbf7b3f35,0x3e48bf35,0x3e48bf35,0x3f7bbf35,0xbf0e3f6d,0xbf553ec4,0xbf553ec4,0x3f0ebf6d,
0xbef10000,0x3f62bf80,0x3f75bf35,0xbe953f35,0xbf7f3f55,0x3dc9bf0e,0x3f46bf7b,0x3f22be48,0xbf223f6d,0xbf463ec4,0xbdc9bec4,0x3f7fbf6d,
0x3e953e48,0xbf753f7b,0xbf623f0e,0x3ef1bf55,0xbf6d3f80,0xbec48000,0x3f6dbf80,0x3ec48000,0xbec43f35,0xbf6d3f35,0x3ec4bf35,0x3f6dbf35,
0x3ec40000,0xbf6d3f80,0xbec40000,0x3f6dbf80,0x3f6dbf35,0xbec43f35,0xbf6d3f35,0x3ec4bf35,0x3e950000,0xbf753f80,0x3ef1bf35,0x3f62bf35,
0x3f46bf0e,0xbf223f55,0xbdc9be48,0x3f7fbf7b,0x3f7fbf6d,0xbdc93ec4,0xbf223ec4,0x3f46bf6d,0x3f62bf7b,0x3ef1be48,0xbf753f55,0x3e95bf0e,
0x3f7bbf80,0x3e488000,0xbe480000,0x3f7bbf80,0x3f55bf6d,0x3f0ebec4,0xbf0e3ec4,0x3f55bf6d,0x3f0ebf35,0x3f55bf35,0xbf553f35,0x3f0ebf35,
0x3e48bec4,0x3f7bbf6d,0xbf7b3f6d,0x3e48bec4,0xbdc90000,0x3f7fbf80,0xbf463f35,0x3f22bf35,0xbe953e48,0x3f75bf7b,0xbf623f55,0x3ef1bf0e,
0xbef13ec4,0x3f62bf6d,0xbf753f6d,0x3e95bec4,0xbf223f0e,0x3f46bf55,0xbf7f3f7b,0x3dc9be48,0x3f803f80,0xbf353f35,0x3f803f80,0xbf353f35,
0x3f803f80,0xbf353f35,0x3f803f80,0xbf353f35,0x3f803f80,0xbf353f35,0x3f803f80,0xbf353f35,0x3f803f80,0xbf353f35,0x3f803f80,0xbf353f35,
0x3f7e3f80,0xbdfbbcc9,0x3f1d3f31,0xbf4abf39,0x3f733f7a,0xbea1be60,0x3ee63f09,0xbf65bf58,0x3f5f3f6a,0xbefcbecf,0x3e893eb8,0xbf77bf6f,
0x3f423f51,0xbf27bf13,0x3d973e2f,0xbf7fbf7c,0x3f783f80,0xbe79bd49,0xbe79bd49,0xbf78bf80,0x3f4e3f67,0xbf18bedb,0xbf18bedb,0xbf4ebf67,
0x3f043f2c,0xbf5cbf3e,0xbf5cbf3e,0xbf04bf2c,0x3e163eac,0xbf7dbf71,0xbf7dbf71,0xbe16beac,0x3f6f3f7f,0xbeb8bd97,0xbf6abf42,0xbecfbf27,
0x3f133f4a,0xbf51bf1d,0xbf7cbf7e,0x3e2fbdfb,0x3cc93ea1,0xbf80bf73,0xbf39bf65,0x3f313ee6,0xbf09be89,0xbf58bf77,0xbe60befc,0x3f7a3f5f,
0x3f623f7f,0xbef1bdc9,0xbf62bf7f,0x3ef13dc9,0x3e953f22,0xbf75bf46,0xbe95bf22,0x3f753f46,0xbef1bdc9,0xbf62bf7f,0x3ef13dc9,0x3f623f7f,
0xbf75bf46,0xbe95bf22,0x3f753f46,0x3e953f22,0x3f513f7e,0xbf13bdfb,0xbe2fbf1d,0x3f7c3f4a,0xbcc93ee6,0xbf80bf65,0x3f393ea1,0x3f313f73,
0xbf58befc,0xbf09bf5f,0x3f7a3f77,0xbe603e89,0xbf6abf7f,0x3ecfbd97,0x3eb83f42,0xbf6fbf27,0x3f3e3f7d,0xbf2cbe16,0x3f2c3e16,0x3f3e3f7d,
0xbeac3e79,0xbf71bf78,0x3f713f78,0xbeac3e79,0xbf80bf4e,0xbd49bf18,0x3d493f18,0xbf80bf4e,0xbedbbf5c,0x3f673f04,0xbf67bf04,0xbedbbf5c,
0x3f273f7c,0xbf42be2f,0x3f7f3f51,0xbd973f13,0xbf1d3cc9,0xbf4abf80,0x3dfb3f39,0xbf7ebf31,0xbf65bf7a,0x3ee6be60,0xbf73bf09,0xbea1bf58,
0x3e89becf,0x3f773f6a,0xbefcbf6f,0x3f5f3eb8,0x3f0e3f7b,0xbf55be48,0x3f0e3f7b,0xbf55be48,0xbf55be48,0xbf0ebf7b,0xbf55be48,0xbf0ebf7b,
0xbf0ebf7b,0x3f553e48,0xbf0ebf7b,0x3f553e48,0x3f553e48,0x3f0e3f7b,0x3f553e48,0x3f0e3f7b,0x3ee63f7a,0xbf65be60,0xbea13f09,0xbf73bf58,
0xbf77becf,0xbe89bf6a,0xbf5fbf6f,0x3efcbeb8,0xbd97bf51,0x3f7f3f13,0x3f27be2f,0x3f423f7c,0x3f7e3f39,0xbdfb3f31,0x3f1d3f80,0xbf4abcc9,
0x3eac3f78,0xbf71be79,0xbf71be79,0xbeacbf78,0xbf80bf18,0x3d49bf4e,0x3d49bf4e,0x3f803f18,0x3edbbf04,0x3f673f5c,0x3f673f5c,0xbedb3f04,
0x3f2c3f7d,0xbf3e3e16,0xbf3e3e16,0xbf2cbf7d,0x3e603f77,0xbf7abe89,0xbf58bf5f,0x3f09befc,0xbf6fbf42,0x3eb8bf27,0x3f6a3d97,0x3ecf3f7f,
0x3f51bdfb,0x3f133f7e,0xbe2f3f4a,0xbf7cbf1d,0x3cc93f65,0xbf80bee6,0xbf39bf73,0x3f31bea1,0x3dc93f75,0xbf7fbe95,0xbdc9bf75,0x3f7f3e95,
0xbf46bf62,0x3f22bef1,0x3f463f62,0xbf223ef1,0x3f7f3e95,0x3dc93f75,0xbf7fbe95,0xbdc9bf75,0xbf223ef1,0xbf46bf62,0x3f22bef1,0x3f463f62,
0xbcc93f73,0xbf80bea1,0x3f39bee6,0x3f313f65,0xbf09bf77,0x3f58be89,0xbe603f5f,0xbf7abefc,0x3f6a3f27,0xbecf3f42,0xbeb8bf7f,0x3f6fbd97,
0xbf7cbdfb,0xbe2fbf7e,0x3f513f4a,0xbf133f1d,0xbe163f71,0xbf7dbeac,0x3f7d3eac,0xbe163f71,0xbe79bf80,0x3f78bd49,0xbf783d49,0xbe79bf80,
0x3f183f67,0xbf4e3edb,0x3f4ebedb,0x3f183f67,0xbf5cbf2c,0x3f04bf3e,0xbf043f3e,0xbf5cbf2c,0xbe893f6f,0xbf77beb8,0x3efc3f6a,0xbf5f3ecf,
0x3d97bf7c,0x3f7f3e2f,0xbf27bf51,0x3f42bf13,0x3dfb3f80,0xbf7e3cc9,0x3f4a3f31,0xbf1d3f39,0xbea1bf7a,0x3f73be60,0xbf65bf09,0x3ee6bf58,
0xbec43f6d,0xbf6dbec4,0xbec43f6d,0xbf6dbec4,0x3ec4bf6d,0x3f6d3ec4,0x3ec4bf6d,0x3f6d3ec4,0xbec43f6d,0xbf6dbec4,0xbec43f6d,0xbf6dbec4,
0x3ec4bf6d,0x3f6d3ec4,0x3ec4bf6d,0x3f6d3ec4,0xbefc3f6a,0xbf5fbecf,0xbf773eb8,0xbe89bf6f,0x3f27bf51,0x3f423f13,0x3f7fbe2f,0x3d973f7c,
0xbf4a3f31,0xbf1dbf39,0xbf7ebcc9,0x3dfbbf80,0x3f65bf09,0x3ee63f58,0x3f733e60,0xbea13f7a,0xbf183f67,0xbf4ebedb,0xbf4ebedb,0x3f18bf67,
0x3f5cbf2c,0x3f043f3e,0x3f043f3e,0xbf5c3f2c,0xbf7d3eac,0xbe16bf71,0xbe16bf71,0x3f7dbeac,0x3f783d49,0xbe793f80,0xbe793f80,0xbf78bd49,
0xbf313f65,0xbf39bee6,0xbcc9bf73,0x3f80bea1,0x3f7abefc,0x3e603f5f,0xbf093f77,0xbf58be89,0xbf6fbd97,0x3eb8bf7f,0x3f6abf27,0x3ecf3f42,
0x3f133f1d,0xbf513f4a,0xbf7c3dfb,0x3e2fbf7e,0xbf463f62,0xbf22bef1,0x3f46bf62,0x3f223ef1,0x3f7fbe95,0xbdc93f75,0xbf7f3e95,0x3dc9bf75,
0xbf22bef1,0x3f46bf62,0x3f223ef1,0xbf463f62,0xbdc93f75,0xbf7f3e95,0x3dc9bf75,0x3f7fbe95,0xbf583f5f,0xbf09befc,0x3f7abe89,0xbe603f77,
0x3f6abd97,0xbecf3f7f,0xbeb8bf27,0x3f6fbf42,0xbe2fbf4a,0x3f7cbf1d,0xbf133f7e,0xbf51bdfb,0xbf393f73,0xbf31bea1,0x3f80bee6,0xbcc93f65,
0xbf673f5c,0xbedbbf04,0x3edb3f04,0xbf673f5c,0x3f3e3e16,0xbf2c3f7d,0x3f2cbf7d,0x3f3e3e16,0x3eacbf78,0x3f71be79,0xbf713e79,0x3eacbf78,
0xbf803f18,0xbd49bf4e,0x3d493f4e,0xbf803f18,0xbf733f58,0xbea1bf09,0xbee63f7a,0xbf653e60,0x3efc3eb8,0xbf5f3f6f,0x3f77becf,0xbe893f6a,
0x3f42bf7c,0x3f273e2f,0x3d97bf51,0x3f7fbf13,0xbf4a3cc9,0x3f1dbf80,0xbf7e3f39,0xbdfbbf31,0xbf7b3f55,0xbe48bf0e,0xbf7b3f55,0xbe48bf0e,
0x3e483f0e,0xbf7b3f55,0x3e483f0e,0xbf7b3f55,0x3f7bbf55,0x3e483f0e,0x3f7bbf55,0x3e483f0e,0xbe48bf0e,0x3f7bbf55,0xbe48bf0e,0x3f7bbf55,
0xbf7f3f51,0xbd97bf13,0xbf423e2f,0x3f27bf7c,0xbdfb3f39,0xbf7e3f31,0xbf4a3f80,0xbf1dbcc9,0x3f73bf09,0xbea13f58,0x3ee63e60,0xbf653f7a,
0x3efcbf6f,0x3f5fbeb8,0x3f77bf6a,0x3e893ecf,0xbf803f4e,0x3d49bf18,0x3d49bf18,0x3f80bf4e,0xbedb3f5c,0xbf673f04,0xbf673f04,0x3edbbf5c,
0x3f2cbe16,0xbf3e3f7d,0xbf3e3f7d,0xbf2c3e16,0x3f71bf78,0x3eac3e79,0x3eac3e79,0xbf713f78,0xbf7c3f4a,0x3e2fbf1d,0x3f51bf7e,0x3f13bdfb,
0xbf313f73,0xbf393ea1,0xbcc9bee6,0x3f80bf65,0x3e603e89,0xbf7a3f77,0xbf583efc,0x3f09bf5f,0x3f6fbf27,0xbeb83f42,0xbf6a3f7f,0xbecfbd97,
0xbf753f46,0x3e95bf22,0x3f75bf46,0xbe953f22,0xbf623f7f,0xbef13dc9,0x3f62bf7f,0x3ef1bdc9,0xbe953f22,0xbf753f46,0x3e95bf22,0x3f75bf46,
0x3ef1bdc9,0xbf623f7f,0xbef13dc9,0x3f62bf7f,0xbf6a3f42,0x3ecfbf27,0x3eb8bd97,0xbf6f3f7f,0xbf7c3f7e,0xbe2fbdfb,0x3f51bf1d,0xbf133f4a,
0xbf393f65,0xbf313ee6,0x3f80bf73,0xbcc93ea1,0xbe603efc,0xbf7a3f5f,0x3f58bf77,0x3f09be89,0xbf5c3f3e,0x3f04bf2c,0xbf043f2c,0xbf5c3f3e,
0xbf7d3f71,0x3e16beac,0xbe163eac,0xbf7d3f71,0xbf783f80,0xbe793d49,0x3e79bd49,0xbf783f80,0xbf4e3f67,0xbf183edb,0x3f18bedb,0xbf4e3f67,
0xbf4a3f39,0x3f1dbf31,0xbf7e3f80,0xbdfb3cc9,0xbf653f58,0x3ee6bf09,0xbf733f7a,0xbea13e60,0xbf773f6f,0x3e89beb8,0xbf5f3f6a,0xbefc3ecf,
0xbf7f3f7c,0x3d97be2f,0xbf423f51,0xbf273f13,0x3f803f80,0xbf353f35,0x3f803f80,0xbf353f35,0x3f803f80,0xbf353f35,0x3f803f80,0xbf353f35,
0x3f803f80,0xbf353f35,0x3f803f80,0xbf353f35,0x3f803f80,0xbf353f35,0x3f803f80,0xbf353f35,0xbdfbbcc9,0xbf7ebf80,0xbf4abf39,0xbf1dbf31,
0xbea1be60,0xbf73bf7a,0xbf65bf58,0xbee6bf09,0xbefcbecf,0xbf5fbf6a,0xbf77bf6f,0xbe89beb8,0xbf27bf13,0xbf42bf51,0xbf7fbf7c,0xbd97be2f,
0xbf78bf80,0x3e793d49,0x3e793d49,0x3f783f80,0xbf4ebf67,0x3f183edb,0x3f183edb,0x3f4e3f67,0xbf04bf2c,0x3f5c3f3e,0x3f5c3f3e,0x3f043f2c,
0xbe16beac,0x3f7d3f71,0x3f7d3f71,0x3e163eac,0x3eb83d97,0x3f6f3f7f,0x3ecf3f27,0xbf6abf42,0x3f513f1d,0x3f133f4a,0xbe2f3dfb,0xbf7cbf7e,
0x3f803f73,0x3cc93ea1,0xbf31bee6,0xbf39bf65,0x3f583f77,0xbf09be89,0xbf7abf5f,0xbe60befc,0x3f623f7f,0xbef1bdc9,0xbf62bf7f,0x3ef13dc9,
0x3e953f22,0xbf75bf46,0xbe95bf22,0x3f753f46,0xbef1bdc9,0xbf62bf7f,0x3ef13dc9,0x3f623f7f,0xbf75bf46,0xbe95bf22,0x3f753f46,0x3e953f22,
0xbf13bdfb,0xbf51bf7e,0x3f7c3f4a,0x3e2f3f1d,0xbf80bf65,0x3cc9bee6,0x3f313f73,0xbf39bea1,0xbf09bf5f,0x3f583efc,0xbe603e89,0xbf7abf77,
0x3ecfbd97,0x3f6a3f7f,0xbf6fbf27,0xbeb8bf42,0xbf3ebf7d,0x3f2c3e16,0xbf2cbe16,0xbf3ebf7d,0x3eacbe79,0x3f713f78,0xbf71bf78,0x3eacbe79,
0x3f803f4e,0x3d493f18,0xbd49bf18,0x3f803f4e,0x3edb3f5c,0xbf67bf04,0x3f673f04,0x3edb3f5c,0x3f423e2f,0x3f273f7c,0x3d97bf13,0x3f7f3f51,
0x3f4a3f80,0xbf1d3cc9,0x3f7e3f31,0x3dfb3f39,0xbee63e60,0xbf65bf7a,0x3ea13f58,0xbf73bf09,0xbf77bf6a,0x3e89becf,0xbf5fbeb8,0xbefcbf6f,
0x3f0e3f7b,0xbf55be48,0x3f0e3f7b,0xbf55be48,0xbf55be48,0xbf0ebf7b,0xbf55be48,0xbf0ebf7b,0xbf0ebf7b,0x3f553e48,0xbf0ebf7b,0x3f553e48,
0x3f553e48,0x3f0e3f7b,0x3f553e48,0x3f0e3f7b,0xbf65be60,0xbee6bf7a,0xbf73bf58,0x3ea1bf09,0xbe89bf6a,0x3f773ecf,0x3efcbeb8,0x3f5f3f6f,
0x3f7f3f13,0x3d973f51,0x3f423f7c,0xbf273e2f,0xbdfb3f31,0xbf7ebf39,0xbf4abcc9,0xbf1dbf80,0xbeacbf78,0x3f713e79,0x3f713e79,0x3eac3f78,
0x3f803f18,0xbd493f4e,0xbd493f4e,0xbf80bf18,0xbedb3f04,0xbf67bf5c,0xbf67bf5c,0x3edbbf04,0xbf2cbf7d,0x3f3ebe16,0x3f3ebe16,0x3f2c3f7d,
0x3f7a3e89,0x3e603f77,0xbf093efc,0xbf58bf5f,0xbeb83f27,0xbf6fbf42,0xbecfbf7f,0x3f6a3d97,0xbf13bf7e,0x3f51bdfb,0x3f7c3f1d,0xbe2f3f4a,
0x3f803ee6,0x3cc93f65,0xbf313ea1,0xbf39bf73,0x3dc93f75,0xbf7fbe95,0xbdc9bf75,0x3f7f3e95,0xbf46bf62,0x3f22bef1,0x3f463f62,0xbf223ef1,
0x3f7f3e95,0x3dc93f75,0xbf7fbe95,0xbdc9bf75,0xbf223ef1,0xbf46bf62,0x3f22bef1,0x3f463f62,0xbf80bea1,0x3cc9bf73,0x3f313f65,0xbf393ee6,
0x3f58be89,0x3f093f77,0xbf7abefc,0x3e60bf5f,0xbecf3f42,0xbf6abf27,0x3f6fbd97,0x3eb83f7f,0xbe2fbf7e,0x3f7c3dfb,0xbf133f1d,0xbf51bf4a,
0x3e16bf71,0x3f7d3eac,0xbf7dbeac,0x3e16bf71,0x3e793f80,0xbf783d49,0x3f78bd49,0x3e793f80,0xbf18bf67,0x3f4ebedb,0xbf4e3edb,0xbf18bf67,
0x3f5c3f2c,0xbf043f3e,0x3f04bf3e,0x3f5c3f2c,0x3f773eb8,0xbe893f6f,0x3f5fbecf,0x3efc3f6a,0xbf7fbe2f,0x3d97bf7c,0xbf423f13,0xbf27bf51,
0x3f7ebcc9,0x3dfb3f80,0x3f1dbf39,0x3f4a3f31,0xbf733e60,0xbea1bf7a,0xbee63f58,0xbf65bf09,0xbec43f6d,0xbf6dbec4,0xbec43f6d,0xbf6dbec4,
0x3ec4bf6d,0x3f6d3ec4,0x3ec4bf6d,0x3f6d3ec4,0xbec43f6d,0xbf6dbec4,0xbec43f6d,0xbf6dbec4,0x3ec4bf6d,0x3f6d3ec4,0x3ec4bf6d,0x3f6d3ec4,
0xbf5fbecf,0x3efcbf6a,0xbe89bf6f,0x3f77beb8,0x3f423f13,0xbf273f51,0x3d973f7c,0xbf7f3e2f,0xbf1dbf39,0x3f4abf31,0x3dfbbf80,0x3f7e3cc9,
0x3ee63f58,0xbf653f09,0xbea13f7a,0xbf73be60,0x3f18bf67,0x3f4e3edb,0x3f4e3edb,0xbf183f67,0xbf5c3f2c,0xbf04bf3e,0xbf04bf3e,0x3f5cbf2c,
0x3f7dbeac,0x3e163f71,0x3e163f71,0xbf7d3eac,0xbf78bd49,0x3e79bf80,0x3e79bf80,0x3f783d49,0x3f393ee6,0xbf313f65,0xbf803ea1,0xbcc9bf73,
0xbe60bf5f,0x3f7abefc,0x3f583e89,0xbf093f77,0xbeb83f7f,0xbf6fbd97,0xbecfbf42,0x3f6abf27,0x3f51bf4a,0x3f133f1d,0xbe2f3f7e,0xbf7c3dfb,
0xbf463f62,0xbf22bef1,0x3f46bf62,0x3f223ef1,0x3f7fbe95,0xbdc93f75,0xbf7f3e95,0x3dc9bf75,0xbf22bef1,0x3f46bf62,0x3f223ef1,0xbf463f62,
0xbdc93f75,0xbf7f3e95,0x3dc9bf75,0x3f7fbe95,0xbf09befc,0x3f58bf5f,0xbe603f77,0xbf7a3e89,0xbecf3f7f,0xbf6a3d97,0x3f6fbf42,0x3eb83f27,
0x3f7cbf1d,0x3e2f3f4a,0xbf51bdfb,0x3f13bf7e,0xbf31bea1,0x3f39bf73,0xbcc93f65,0xbf803ee6,0x3f67bf5c,0x3edb3f04,0xbedbbf04,0x3f67bf5c,
0xbf3ebe16,0x3f2cbf7d,0xbf2c3f7d,0xbf3ebe16,0xbeac3f78,0xbf713e79,0x3f71be79,0xbeac3f78,0x3f80bf18,0x3d493f4e,0xbd49bf4e,0x3f80bf18,
0x3ea13f09,0xbf733f58,0x3f65be60,0xbee63f7a,0x3f5fbf6f,0x3efc3eb8,0x3e89bf6a,0x3f77becf,0xbf27be2f,0x3f42bf7c,0xbf7f3f13,0x3d97bf51,
0xbf1d3f80,0xbf4a3cc9,0x3dfb3f31,0xbf7e3f39,0xbf7b3f55,0xbe48bf0e,0xbf7b3f55,0xbe48bf0e,0x3e483f0e,0xbf7b3f55,0x3e483f0e,0xbf7b3f55,
0x3f7bbf55,0x3e483f0e,0x3f7bbf55,0x3e483f0e,0xbe48bf0e,0x3f7bbf55,0xbe48bf0e,0x3f7bbf55,0xbd97bf13,0x3f7fbf51,0x3f27bf7c,0x3f42be2f,
0xbf7e3f31,0x3dfbbf39,0xbf1dbcc9,0x3f4abf80,0xbea13f58,0xbf733f09,0xbf653f7a,0xbee6be60,0x3f5fbeb8,0xbefc3f6f,0x3e893ecf,0xbf773f6a,
0x3f80bf4e,0xbd493f18,0xbd493f18,0xbf803f4e,0x3edbbf5c,0x3f67bf04,0x3f67bf04,0xbedb3f5c,0xbf2c3e16,0x3f3ebf7d,0x3f3ebf7d,0x3f2cbe16,
0xbf713f78,0xbeacbe79,0xbeacbe79,0x3f71bf78,0xbe2f3f1d,0xbf7c3f4a,0xbf133dfb,0x3f51bf7e,0x3f39bea1,0xbf313f73,0xbf803f65,0xbcc9bee6,
0x3f7abf77,0x3e603e89,0xbf093f5f,0xbf583efc,0x3eb8bf42,0x3f6fbf27,0x3ecf3d97,0xbf6a3f7f,0xbf753f46,0x3e95bf22,0x3f75bf46,0xbe953f22,
0xbf623f7f,0xbef13dc9,0x3f62bf7f,0x3ef1bdc9,0xbe953f22,0xbf753f46,0x3e95bf22,0x3f75bf46,0x3ef1bdc9,0xbf623f7f,0xbef13dc9,0x3f62bf7f,
0x3ecfbf27,0x3f6abf42,0xbf6f3f7f,0xbeb83d97,0xbe2fbdfb,0x3f7cbf7e,0xbf133f4a,0xbf513f1d,0xbf313ee6,0x3f39bf65,0xbcc93ea1,0xbf803f73,
0xbf7a3f5f,0x3e60befc,0x3f09be89,0xbf583f77,0x3f5cbf3e,0xbf043f2c,0x3f04bf2c,0x3f5cbf3e,0x3f7dbf71,0xbe163eac,0x3e16beac,0x3f7dbf71,
0x3f78bf80,0x3e79bd49,0xbe793d49,0x3f78bf80,0x3f4ebf67,0x3f18bedb,0xbf183edb,0x3f4ebf67,0xbf1d3f31,0xbf4a3f39,0x3dfbbcc9,0xbf7e3f80,
0xbee63f09,0xbf653f58,0x3ea1be60,0xbf733f7a,0xbe893eb8,0xbf773f6f,0x3efcbecf,0xbf5f3f6a,0xbd973e2f,0xbf7f3f7c,0x3f27bf13,0xbf423f51,
0x3f803f80,0xbf353f35,0x3f803f80,0xbf353f35,0x3f803f80,0xbf353f35,0x3f803f80,0xbf353f35,0x3f803f80,0xbf353f35,0x3f803f80,0xbf353f35,
0x3f803f80,0xbf353f35,0x3f803f80,0xbf353f35,0xbf7ebf80,0x3dfb3cc9,0xbf1dbf31,0x3f4a3f39,0xbf73bf7a,0x3ea13e60,0xbee6bf09,0x3f653f58,
0xbf5fbf6a,0x3efc3ecf,0xbe89beb8,0x3f773f6f,0xbf42bf51,0x3f273f13,0xbd97be2f,0x3f7f3f7c,0x3f783f80,0xbe79bd49,0xbe79bd49,0xbf78bf80,
0x3f4e3f67,0xbf18bedb,0xbf18bedb,0xbf4ebf67,0x3f043f2c,0xbf5cbf3e,0xbf5cbf3e,0xbf04bf2c,0x3e163eac,0xbf7dbf71,0xbf7dbf71,0xbe16beac,
0xbf6fbf7f,0x3eb83d97,0x3f6a3f42,0x3ecf3f27,0xbf13bf4a,0x3f513f1d,0x3f7c3f7e,0xbe2f3dfb,0xbcc9bea1,0x3f803f73,0x3f393f65,0xbf31bee6,
0x3f093e89,0x3f583f77,0x3e603efc,0xbf7abf5f,0x3f623f7f,0xbef1bdc9,0xbf62bf7f,0x3ef13dc9,0x3e953f22,0xbf75bf46,0xbe95bf22,0x3f753f46,
0xbef1bdc9,0xbf62bf7f,0x3ef13dc9,0x3f623f7f,0xbf75bf46,0xbe95bf22,0x3f753f46,0x3e953f22,0xbf51bf7e,0x3f133dfb,0x3e2f3f1d,0xbf7cbf4a,
0x3cc9bee6,0x3f803f65,0xbf39bea1,0xbf31bf73,0x3f583efc,0x3f093f5f,0xbf7abf77,0x3e60be89,0x3f6a3f7f,0xbecf3d97,0xbeb8bf42,0x3f6f3f27,
0x3f3e3f7d,0xbf2cbe16,0x3f2c3e16,0x3f3e3f7d,0xbeac3e79,0xbf71bf78,0x3f713f78,0xbeac3e79,0xbf80bf4e,0xbd49bf18,0x3d493f18,0xbf80bf4e,
0xbedbbf5c,0x3f673f04,0xbf67bf04,0xbedbbf5c,0xbf27bf7c,0x3f423e2f,0xbf7fbf51,0x3d97bf13,0x3f1dbcc9,0x3f4a3f80,0xbdfbbf39,0x3f7e3f31,
0x3f653f7a,0xbee63e60,0x3f733f09,0x3ea13f58,0xbe893ecf,0xbf77bf6a,0x3efc3f6f,0xbf5fbeb8,0x3f0e3f7b,0xbf55be48,0x3f0e3f7b,0xbf55be48,
0xbf55be48,0xbf0ebf7b,0xbf55be48,0xbf0ebf7b,0xbf0ebf7b,0x3f553e48,0xbf0ebf7b,0x3f553e48,0x3f553e48,0x3f0e3f7b,0x3f553e48,0x3f0e3f7b,
0xbee6bf7a,0x3f653e60,0x3ea1bf09,0x3f733f58,0x3f773ecf,0x3e893f6a,0x3f5f3f6f,0xbefc3eb8,0x3d973f51,0xbf7fbf13,0xbf273e2f,0xbf42bf7c,
0xbf7ebf39,0x3dfbbf31,0xbf1dbf80,0x3f4a3cc9,0x3eac3f78,0xbf71be79,0xbf71be79,0xbeacbf78,0xbf80bf18,0x3d49bf4e,0x3d49bf4e,0x3f803f18,
0x3edbbf04,0x3f673f5c,0x3f673f5c,0xbedb3f04,0x3f2c3f7d,0xbf3e3e16,0xbf3e3e16,0xbf2cbf7d,0xbe60bf77,0x3f7a3e89,0x3f583f5f,0xbf093efc,
0x3f6f3f42,0xbeb83f27,0xbf6abd97,0xbecfbf7f,0xbf513dfb,0xbf13bf7e,0x3e2fbf4a,0x3f7c3f1d,0xbcc9bf65,0x3f803ee6,0x3f393f73,0xbf313ea1,
0x3dc93f75,0xbf7fbe95,0xbdc9bf75,0x3f7f3e95,0xbf46bf62,0x3f22bef1,0x3f463f62,0xbf223ef1,0x3f7f3e95,0x3dc93f75,0xbf7fbe95,0xbdc9bf75,
0xbf223ef1,0xbf46bf62,0x3f22bef1,0x3f463f62,0x3cc9bf73,0x3f803ea1,0xbf393ee6,0xbf31bf65,0x3f093f77,0xbf583e89,0x3e60bf5f,0x3f7a3efc,
0xbf6abf27,0x3ecfbf42,0x3eb83f7f,0xbf6f3d97,0x3f7c3dfb,0x3e2f3f7e,0xbf51bf4a,0x3f13bf1d,0xbe163f71,0xbf7dbeac,0x3f7d3eac,0xbe163f71,
0xbe79bf80,0x3f78bd49,0xbf783d49,0xbe79bf80,0x3f183f67,0xbf4e3edb,0x3f4ebedb,0x3f183f67,0xbf5cbf2c,0x3f04bf3e,0xbf043f3e,0xbf5cbf2c,
0x3e89bf6f,0x3f773eb8,0xbefcbf6a,0x3f5fbecf,0xbd973f7c,0xbf7fbe2f,0x3f273f51,0xbf423f13,0xbdfbbf80,0x3f7ebcc9,0xbf4abf31,0x3f1dbf39,
0x3ea13f7a,0xbf733e60,0x3f653f09,0xbee63f58,0xbec43f6d,0xbf6dbec4,0xbec43f6d,0xbf6dbec4,0x3ec4bf6d,0x3f6d3ec4,0x3ec4bf6d,0x3f6d3ec4,
0xbec43f6d,0xbf6dbec4,0xbec43f6d,0xbf6dbec4,0x3ec4bf6d,0x3f6d3ec4,0x3ec4bf6d,0x3f6d3ec4,0x3efcbf6a,0x3f5f3ecf,0x3f77beb8,0x3e893f6f,
0xbf273f51,0xbf42bf13,0xbf7f3e2f,0xbd97bf7c,0x3f4abf31,0x3f1d3f39,0x3f7e3cc9,0xbdfb3f80,0xbf653f09,0xbee6bf58,0xbf73be60,0x3ea1bf7a,
0xbf183f67,0xbf4ebedb,0xbf4ebedb,0x3f18bf67,0x3f5cbf2c,0x3f043f3e,0x3f043f3e,0xbf5c3f2c,0xbf7d3eac,0xbe16bf71,0xbe16bf71,0x3f7dbeac,
0x3f783d49,0xbe793f80,0xbe793f80,0xbf78bd49,0x3f31bf65,0x3f393ee6,0x3cc93f73,0xbf803ea1,0xbf7a3efc,0xbe60bf5f,0x3f09bf77,0x3f583e89,
0x3f6f3d97,0xbeb83f7f,0xbf6a3f27,0xbecfbf42,0xbf13bf1d,0x3f51bf4a,0x3f7cbdfb,0xbe2f3f7e,0xbf463f62,0xbf22bef1,0x3f46bf62,0x3f223ef1,
0x3f7fbe95,0xbdc93f75,0xbf7f3e95,0x3dc9bf75,0xbf22bef1,0x3f46bf62,0x3f223ef1,0xbf463f62,0xbdc93f75,0xbf7f3e95,0x3dc9bf75,0x3f7fbe95,
0x3f58bf5f,0x3f093efc,0xbf7a3e89,0x3e60bf77,0xbf6a3d97,0x3ecfbf7f,0x3eb83f27,0xbf6f3f42,0x3e2f3f4a,0xbf7c3f1d,0x3f13bf7e,0x3f513dfb,
0x3f39bf73,0x3f313ea1,0xbf803ee6,0x3cc9bf65,0xbf673f5c,0xbedbbf04,0x3edb3f04,0xbf673f5c,0x3f3e3e16,0xbf2c3f7d,0x3f2cbf7d,0x3f3e3e16,
0x3eacbf78,0x3f71be79,0xbf713e79,0x3eacbf78,0xbf803f18,0xbd49bf4e,0x3d493f4e,0xbf803f18,0x3f73bf58,0x3ea13f09,0x3ee6bf7a,0x3f65be60,
0xbefcbeb8,0x3f5fbf6f,0xbf773ecf,0x3e89bf6a,0xbf423f7c,0xbf27be2f,0xbd973f51,0xbf7f3f13,0x3f4abcc9,0xbf1d3f80,0x3f7ebf39,0x3dfb3f31,
0xbf7b3f55,0xbe48bf0e,0xbf7b3f55,0xbe48bf0e,0x3e483f0e,0xbf7b3f55,0x3e483f0e,0xbf7b3f55,0x3f7bbf55,0x3e483f0e,0x3f7bbf55,0x3e483f0e,
0xbe48bf0e,0x3f7bbf55,0xbe48bf0e,0x3f7bbf55,0x3f7fbf51,0x3d973f13,0x3f42be2f,0xbf273f7c,0x3dfbbf39,0x3f7ebf31,0x3f4abf80,0x3f1d3cc9,
0xbf733f09,0x3ea1bf58,0xbee6be60,0x3f65bf7a,0xbefc3f6f,0xbf5f3eb8,0xbf773f6a,0xbe89becf,0xbf803f4e,0x3d49bf18,0x3d49bf18,0x3f80bf4e,
0xbedb3f5c,0xbf673f04,0xbf673f04,0x3edbbf5c,0x3f2cbe16,0xbf3e3f7d,0xbf3e3f7d,0xbf2c3e16,0x3f71bf78,0x3eac3e79,0x3eac3e79,0xbf713f78,
0x3f7cbf4a,0xbe2f3f1d,0xbf513f7e,0xbf133dfb,0x3f31bf73,0x3f39bea1,0x3cc93ee6,0xbf803f65,0xbe60be89,0x3f7abf77,0x3f58befc,0xbf093f5f,
0xbf6f3f27,0x3eb8bf42,0x3f6abf7f,0x3ecf3d97,0xbf753f46,0x3e95bf22,0x3f75bf46,0xbe953f22,0xbf623f7f,0xbef13dc9,0x3f62bf7f,0x3ef1bdc9,
0xbe953f22,0xbf753f46,0x3e95bf22,0x3f75bf46,0x3ef1bdc9,0xbf623f7f,0xbef13dc9,0x3f62bf7f,0x3f6abf42,0xbecf3f27,0xbeb83d97,0x3f6fbf7f,
0x3f7cbf7e,0x3e2f3dfb,0xbf513f1d,0x3f13bf4a,0x3f39bf65,0x3f31bee6,0xbf803f73,0x3cc9bea1,0x3e60befc,0x3f7abf5f,0xbf583f77,0xbf093e89,
0xbf5c3f3e,0x3f04bf2c,0xbf043f2c,0xbf5c3f3e,0xbf7d3f71,0x3e16beac,0xbe163eac,0xbf7d3f71,0xbf783f80,0xbe793d49,0x3e79bd49,0xbf783f80,
0xbf4e3f67,0xbf183edb,0x3f18bedb,0xbf4e3f67,0x3f4abf39,0xbf1d3f31,0x3f7ebf80,0x3dfbbcc9,0x3f65bf58,0xbee63f09,0x3f73bf7a,0x3ea1be60,
0x3f77bf6f,0xbe893eb8,0x3f5fbf6a,0x3efcbecf,0x3f7fbf7c,0xbd973e2f,0x3f42bf51,0x3f27bf13,0x3f803f80,0xbf353f35,0x3f803f80,0xbf353f35,
0x3f803f80,0xbf353f35,0x3f803f80,0xbf353f35,0x3f803f80,0xbf353f35,0x3f803f80,0xbf353f35,0x3f803f80,0xbf353f35,0x3f803f80,0xbf353f35,
0x3dfb3cc9,0x3f7e3f80,0x3f4a3f39,0x3f1d3f31,0x3ea13e60,0x3f733f7a,0x3f653f58,0x3ee63f09,0x3efc3ecf,0x3f5f3f6a,0x3f773f6f,0x3e893eb8,
0x3f273f13,0x3f423f51,0x3f7f3f7c,0x3d973e2f,0xbf78bf80,0x3e793d49,0x3e793d49,0x3f783f80,0xbf4ebf67,0x3f183edb,0x3f183edb,0x3f4e3f67,
0xbf04bf2c,0x3f5c3f3e,0x3f5c3f3e,0x3f043f2c,0xbe16beac,0x3f7d3f71,0x3f7d3f71,0x3e163eac,0xbeb8bd97,0xbf6fbf7f,0xbecfbf27,0x3f6a3f42,
0xbf51bf1d,0xbf13bf4a,0x3e2fbdfb,0x3f7c3f7e,0xbf80bf73,0xbcc9bea1,0x3f313ee6,0x3f393f65,0xbf58bf77,0x3f093e89,0x3f7a3f5f,0x3e603efc,
0x3f623f7f,0xbef1bdc9,0xbf62bf7f,0x3ef13dc9,0x3e953f22,0xbf75bf46,0xbe95bf22,0x3f753f46,0xbef1bdc9,0xbf62bf7f,0x3ef13dc9,0x3f623f7f,
0xbf75bf46,0xbe95bf22,0x3f753f46,0x3e953f22,0x3f133dfb,0x3f513f7e,0xbf7cbf4a,0xbe2fbf1d,0x3f803f65,0xbcc93ee6,0xbf31bf73,0x3f393ea1,
0x3f093f5f,0xbf58befc,0x3e60be89,0x3f7a3f77,0xbecf3d97,0xbf6abf7f,0x3f6f3f27,0x3eb83f42,0xbf3ebf7d,0x3f2c3e16,0xbf2cbe16,0xbf3ebf7d,
0x3eacbe79,0x3f713f78,0xbf71bf78,0x3eacbe79,0x3f803f4e,0x3d493f18,0xbd49bf18,0x3f803f4e,0x3edb3f5c,0xbf67bf04,0x3f673f04,0x3edb3f5c,
0xbf42be2f,0xbf27bf7c,0xbd973f13,0xbf7fbf51,0xbf4abf80,0x3f1dbcc9,0xbf7ebf31,0xbdfbbf39,0x3ee6be60,0x3f653f7a,0xbea1bf58,0x3f733f09,
0x3f773f6a,0xbe893ecf,0x3f5f3eb8,0x3efc3f6f,0x3f0e3f7b,0xbf55be48,0x3f0e3f7b,0xbf55be48,0xbf55be48,0xbf0ebf7b,0xbf55be48,0xbf0ebf7b,
0xbf0ebf7b,0x3f553e48,0xbf0ebf7b,0x3f553e48,0x3f553e48,0x3f0e3f7b,0x3f553e48,0x3f0e3f7b,0x3f653e60,0x3ee63f7a,0x3f733f58,0xbea13f09,
0x3e893f6a,0xbf77becf,0xbefc3eb8,0xbf5fbf6f,0xbf7fbf13,0xbd97bf51,0xbf42bf7c,0x3f27be2f,0x3dfbbf31,0x3f7e3f39,0x3f4a3cc9,0x3f1d3f80,
0xbeacbf78,0x3f713e79,0x3f713e79,0x3eac3f78,0x3f803f18,0xbd493f4e,0xbd493f4e,0xbf80bf18,0xbedb3f04,0xbf67bf5c,0xbf67bf5c,0x3edbbf04,
0xbf2cbf7d,0x3f3ebe16,0x3f3ebe16,0x3f2c3f7d,0xbf7abe89,0xbe60bf77,0x3f09befc,0x3f583f5f,0x3eb8bf27,0x3f6f3f42,0x3ecf3f7f,0xbf6abd97,
0x3f133f7e,0xbf513dfb,0xbf7cbf1d,0x3e2fbf4a,0xbf80bee6,0xbcc9bf65,0x3f31bea1,0x3f393f73,0x3dc93f75,0xbf7fbe95,0xbdc9bf75,0x3f7f3e95,
0xbf46bf62,0x3f22bef1,0x3f463f62,0xbf223ef1,0x3f7f3e95,0x3dc93f75,0xbf7fbe95,0xbdc9bf75,0xbf223ef1,0xbf46bf62,0x3f22bef1,0x3f463f62,
0x3f803ea1,0xbcc93f73,0xbf31bf65,0x3f39bee6,0xbf583e89,0xbf09bf77,0x3f7a3efc,0xbe603f5f,0x3ecfbf42,0x3f6a3f27,0xbf6f3d97,0xbeb8bf7f,
0x3e2f3f7e,0xbf7cbdfb,0x3f13bf1d,0x3f513f4a,0x3e16bf71,0x3f7d3eac,0xbf7dbeac,0x3e16bf71,0x3e793f80,0xbf783d49,0x3f78bd49,0x3e793f80,
0xbf18bf67,0x3f4ebedb,0xbf4e3edb,0xbf18bf67,0x3f5c3f2c,0xbf043f3e,0x3f04bf3e,0x3f5c3f2c,0xbf77beb8,0x3e89bf6f,0xbf5f3ecf,0xbefcbf6a,
0x3f7f3e2f,0xbd973f7c,0x3f42bf13,0x3f273f51,0xbf7e3cc9,0xbdfbbf80,0xbf1d3f39,0xbf4abf31,0x3f73be60,0x3ea13f7a,0x3ee6bf58,0x3f653f09,
0xbec43f6d,0xbf6dbec4,0xbec43f6d,0xbf6dbec4,0x3ec4bf6d,0x3f6d3ec4,0x3ec4bf6d,0x3f6d3ec4,0xbec43f6d,0xbf6dbec4,0xbec43f6d,0xbf6dbec4,
0x3ec4bf6d,0x3f6d3ec4,0x3ec4bf6d,0x3f6d3ec4,0x3f5f3ecf,0xbefc3f6a,0x3e893f6f,0xbf773eb8,0xbf42bf13,0x3f27bf51,0xbd97bf7c,0x3f7fbe2f,
0x3f1d3f39,0xbf4a3f31,0xbdfb3f80,0xbf7ebcc9,0xbee6bf58,0x3f65bf09,0x3ea1bf7a,0x3f733e60,0x3f18bf67,0x3f4e3edb,0x3f4e3edb,0xbf183f67,
0xbf5c3f2c,0xbf04bf3e,0xbf04bf3e,0x3f5cbf2c,0x3f7dbeac,0x3e163f71,0x3e163f71,0xbf7d3eac,0xbf78bd49,0x3e79bf80,0x3e79bf80,0x3f783d49,
0xbf39bee6,0x3f31bf65,0x3f80bea1,0x3cc93f73,0x3e603f5f,0xbf7a3efc,0xbf58be89,0x3f09bf77,0x3eb8bf7f,0x3f6f3d97,0x3ecf3f42,0xbf6a3f27,
0xbf513f4a,0xbf13bf1d,0x3e2fbf7e,0x3f7cbdfb,0xbf463f62,0xbf22bef1,0x3f46bf62,0x3f223ef1,0x3f7fbe95,0xbdc93f75,0xbf7f3e95,0x3dc9bf75,
0xbf22bef1,0x3f46bf62,0x3f223ef1,0xbf463f62,0xbdc93f75,0xbf7f3e95,0x3dc9bf75,0x3f7fbe95,0x3f093efc,0xbf583f5f,0x3e60bf77,0x3f7abe89,
0x3ecfbf7f,0x3f6abd97,0xbf6f3f42,0xbeb8bf27,0xbf7c3f1d,0xbe2fbf4a,0x3f513dfb,0xbf133f7e,0x3f313ea1,0xbf393f73,0x3cc9bf65,0x3f80bee6,
0x3f67bf5c,0x3edb3f04,0xbedbbf04,0x3f67bf5c,0xbf3ebe16,0x3f2cbf7d,0xbf2c3f7d,0xbf3ebe16,0xbeac3f78,0xbf713e79,0x3f71be79,0xbeac3f78,
0x3f80bf18,0x3d493f4e,0xbd49bf4e,0x3f80bf18,0xbea1bf09,0x3f73bf58,0xbf653e60,0x3ee6bf7a,0xbf5f3f6f,0xbefcbeb8,0xbe893f6a,0xbf773ecf,
0x3f273e2f,0xbf423f7c,0x3f7fbf13,0xbd973f51,0x3f1dbf80,0x3f4abcc9,0xbdfbbf31,0x3f7ebf39,0xbf7b3f55,0xbe48bf0e,0xbf7b3f55,0xbe48bf0e,
0x3e483f0e,0xbf7b3f55,0x3e483f0e,0xbf7b3f55,0x3f7bbf55,0x3e483f0e,0x3f7bbf55,0x3e483f0e,0xbe48bf0e,0x3f7bbf55,0xbe48bf0e,0x3f7bbf55,
0x3d973f13,0xbf7f3f51,0xbf273f7c,0xbf423e2f,0x3f7ebf31,0xbdfb3f39,0x3f1d3cc9,0xbf4a3f80,0x3ea1bf58,0x3f73bf09,0x3f65bf7a,0x3ee63e60,
0xbf5f3eb8,0x3efcbf6f,0xbe89becf,0x3f77bf6a,0x3f80bf4e,0xbd493f18,0xbd493f18,0xbf803f4e,0x3edbbf5c,0x3f67bf04,0x3f67bf04,0xbedb3f5c,
0xbf2c3e16,0x3f3ebf7d,0x3f3ebf7d,0x3f2cbe16,0xbf713f78,0xbeacbe79,0xbeacbe79,0x3f71bf78,0x3e2fbf1d,0x3f7cbf4a,0x3f13bdfb,0xbf513f7e,
0xbf393ea1,0x3f31bf73,0x3f80bf65,0x3cc93ee6,0xbf7a3f77,0xbe60be89,0x3f09bf5f,0x3f58befc,0xbeb83f42,0xbf6f3f27,0xbecfbd97,0x3f6abf7f,
0xbf753f46,0x3e95bf22,0x3f75bf46,0xbe953f22,0xbf623f7f,0xbef13dc9,0x3f62bf7f,0x3ef1bdc9,0xbe953f22,0xbf753f46,0x3e95bf22,0x3f75bf46,
0x3ef1bdc9,0xbf623f7f,0xbef13dc9,0x3f62bf7f,0xbecf3f27,0xbf6a3f42,0x3f6fbf7f,0x3eb8bd97,0x3e2f3dfb,0xbf7c3f7e,0x3f13bf4a,0x3f51bf1d,
0x3f31bee6,0xbf393f65,0x3cc9bea1,0x3f80bf73,0x3f7abf5f,0xbe603efc,0xbf093e89,0x3f58bf77,0x3f5cbf3e,0xbf043f2c,0x3f04bf2c,0x3f5cbf3e,
0x3f7dbf71,0xbe163eac,0x3e16beac,0x3f7dbf71,0x3f78bf80,0x3e79bd49,0xbe793d49,0x3f78bf80,0x3f4ebf67,0x3f18bedb,0xbf183edb,0x3f4ebf67,
0x3f1dbf31,0x3f4abf39,0xbdfb3cc9,0x3f7ebf80,0x3ee6bf09,0x3f65bf58,0xbea13e60,0x3f73bf7a,0x3e89beb8,0x3f77bf6f,0xbefc3ecf,0x3f5fbf6a,
0x3d97be2f,0x3f7fbf7c,0xbf273f13,0x3f42bf51,0x3f803f80,0xbf803f80,0x3f803f80,0xbf803f80,0x3f803f80,0xbf803f80,0x3f803f80,0xbf803f80,
0x3f803f80,0xbf803f80,0x3f803f80,0xbf803f80,0x3f803f80,0xbf803f80,0x3f803f80,0xbf803f80,0x3f7d3f80,0xbe16bd49,0x3f183f2c,0xbf4ebf3e,
0x3f713f78,0xbeacbe79,0x3edb3f04,0xbf67bf5c,0x3f5c3f67,0xbf04bedb,0x3e793eac,0xbf78bf71,0x3f3e3f4e,0xbf2cbf18,0x3d493e16,0xbf80bf7d,
0x3f753f7f,0xbe95bdc9,0xbe95bdc9,0xbf75bf7f,0x3f463f62,0xbf22bef1,0xbf22bef1,0xbf46bf62,0x3ef13f22,0xbf62bf46,0xbf62bf46,0xbef1bf22,
0x3dc93e95,0xbf7fbf75,0xbf7fbf75,0xbdc9be95,0x3f673f7d,0xbedbbe16,0xbf71bf4e,0xbeacbf18,0x3f043f3e,0xbf5cbf2c,0xbf78bf80,0x3e79bd49,
0xbd493e79,0xbf80bf78,0xbf2cbf5c,0x3f3e3f04,0xbf18beac,0xbf4ebf71,0xbe16bedb,0x3f7d3f67,0x3f553f7b,0xbf0ebe48,0xbf55bf7b,0x3f0e3e48,
0x3e483f0e,0xbf7bbf55,0xbe48bf0e,0x3f7b3f55,0xbf0ebe48,0xbf55bf7b,0x3f0e3e48,0x3f553f7b,0xbf7bbf55,0xbe48bf0e,0x3f7b3f55,0x3e483f0e,
0x3f3e3f78,0xbf2cbe79,0xbd49bf04,0x3f803f5c,0xbe163eac,0xbf7dbf71,0x3f4e3edb,0x3f183f67,0xbf67bf18,0xbedbbf4e,0x3f713f7d,0xbeac3e16,
0xbf5cbf80,0x3f043d49,0x3e793f2c,0xbf78bf3e,0x3f223f75,0xbf46be95,0x3f463e95,0x3f223f75,0xbef13dc9,0xbf62bf7f,0x3f623f7f,0xbef13dc9,
0xbf7fbf62,0x3dc9bef1,0xbdc93ef1,0xbf7fbf62,0xbe95bf46,0x3f753f22,0xbf75bf22,0xbe95bf46,0x3f043f71,0xbf5cbeac,0x3f783f67,0xbe793edb,
0xbf3ebe16,0xbf2cbf7d,0xbd493f18,0xbf80bf4e,0xbf4ebf80,0x3f18bd49,0xbf7dbf2c,0xbe16bf3e,0x3edbbe79,0x3f673f78,0xbeacbf5c,0x3f713f04,
0x3ec43f6d,0xbf6dbec4,0x3ec43f6d,0xbf6dbec4,0xbf6dbec4,0xbec4bf6d,0xbf6dbec4,0xbec4bf6d,0xbec4bf6d,0x3f6d3ec4,0xbec4bf6d,0x3f6d3ec4,
0x3f6d3ec4,0x3ec43f6d,0x3f6d3ec4,0x3ec43f6d,0x3e793f67,0xbf78bedb,0xbf043eac,0xbf5cbf71,0xbf80bf18,0xbd49bf4e,0xbf3ebf7d,0x3f2cbe16,
0x3e16bf2c,0x3f7d3f3e,0x3f4e3d49,0x3f183f80,0x3f713f5c,0xbeac3f04,0x3edb3f78,0xbf67be79,0x3dc93f62,0xbf7fbef1,0xbf7fbef1,0xbdc9bf62,
0xbf75bf46,0x3e95bf22,0x3e95bf22,0x3f753f46,0x3f22be95,0x3f463f75,0x3f463f75,0xbf223e95,0x3ef13f7f,0xbf62bdc9,0xbf62bdc9,0xbef1bf7f,
0xbd493f5c,0xbf80bf04,0xbf2cbf78,0x3f3ebe79,0xbf4ebf67,0x3f18bedb,0x3f7d3eac,0x3e163f71,0x3f713e16,0x3eac3f7d,0xbedb3f18,0xbf67bf4e,
0xbe793f3e,0xbf78bf2c,0xbf04bf80,0x3f5cbd49,0xbe483f55,0xbf7bbf0e,0x3e48bf55,0x3f7b3f0e,0xbf0ebf7b,0x3f55be48,0x3f0e3f7b,0xbf553e48,
0x3f7b3f0e,0xbe483f55,0xbf7bbf0e,0x3e48bf55,0xbf553e48,0xbf0ebf7b,0x3f55be48,0x3f0e3f7b,0xbeac3f4e,0xbf71bf18,0x3f67be16,0x3edb3f7d,
0xbe79bf80,0x3f783d49,0xbf043f2c,0xbf5cbf3e,0x3f3e3f5c,0xbf2c3f04,0xbd49bf78,0x3f803e79,0xbf7dbedb,0x3e16bf67,0x3f183f71,0xbf4e3eac,
0xbef13f46,0xbf62bf22,0x3f623f22,0xbef13f46,0x3dc9bf75,0x3f7f3e95,0xbf7fbe95,0x3dc9bf75,0x3e953f7f,0xbf753dc9,0x3f75bdc9,0x3e953f7f,
0xbf22bf62,0x3f46bef1,0xbf463ef1,0xbf22bf62,0xbf183f3e,0xbf4ebf2c,0x3e163f80,0xbf7d3d49,0x3edbbf5c,0x3f673f04,0xbeacbf78,0x3f71be79,
0xbe793f71,0xbf78beac,0x3f043f67,0xbf5c3edb,0x3d49bf7d,0x3f803e16,0xbf2cbf4e,0x3f3ebf18,0xbf353f35,0xbf35bf35,0xbf353f35,0xbf35bf35,
0x3f35bf35,0x3f353f35,0x3f35bf35,0x3f353f35,0xbf353f35,0xbf35bf35,0xbf353f35,0xbf35bf35,0x3f35bf35,0x3f353f35,0x3f35bf35,0x3f353f35,
0xbf4e3f2c,0xbf18bf3e,0xbf7dbd49,0x3e16bf80,0x3f67bf04,0x3edb3f5c,0x3f713e79,0xbeac3f78,0xbf783eac,0xbe79bf71,0xbf5cbedb,0x3f04bf67,
0x3f80be16,0x3d493f7d,0x3f3e3f18,0xbf2c3f4e,0xbf623f22,0xbef1bf46,0xbef1bf46,0x3f62bf22,0x3f7fbe95,0x3dc93f75,0x3dc93f75,0xbf7f3e95,
0xbf75bdc9,0x3e95bf7f,0x3e95bf7f,0x3f753dc9,0x3f463ef1,0xbf223f62,0xbf223f62,0xbf46bef1,0xbf713f18,0xbeacbf4e,0x3edbbf7d,0x3f673e16,
0x3f78bd49,0xbe793f80,0xbf5c3f3e,0xbf04bf2c,0xbf2cbf04,0x3f3ebf5c,0x3f80be79,0xbd493f78,0x3e163f67,0xbf7d3edb,0xbf4ebeac,0x3f18bf71,
0xbf7b3f0e,0xbe48bf55,0x3f7bbf0e,0x3e483f55,0x3f553e48,0xbf0e3f7b,0xbf55be48,0x3f0ebf7b,0xbe48bf55,0x3f7bbf0e,0x3e483f55,0xbf7b3f0e,
0xbf0e3f7b,0xbf55be48,0x3f0ebf7b,0x3f553e48,0xbf803f04,0xbd49bf5c,0x3f3e3e79,0xbf2c3f78,0x3f183edb,0xbf4e3f67,0x3e16bf71,0x3f7dbeac,
0x3eacbf7d,0x3f71be16,0xbf673f4e,0xbedbbf18,0xbf783f2c,0xbe79bf3e,0x3f5c3d49,0xbf043f80,0xbf7f3ef1,0x3dc9bf62,0xbdc93f62,0xbf7f3ef1,
0x3e953f22,0xbf753f46,0x3f75bf46,0x3e953f22,0x3f46bf75,0x3f223e95,0xbf22be95,0x3f46bf75,0xbf623dc9,0x3ef1bf7f,0xbef13f7f,0xbf623dc9,
0xbf783edb,0x3e79bf67,0xbf5c3f71,0xbf04beac,0xbd493f4e,0xbf803f18,0x3f2c3e16,0xbf3e3f7d,0x3f7dbf3e,0x3e163f2c,0x3f18bf80,0x3f4ebd49,
0xbeacbf04,0x3f71bf5c,0xbf673e79,0x3edbbf78,0xbf6d3ec4,0x3ec4bf6d,0xbf6d3ec4,0x3ec4bf6d,0xbec43f6d,0xbf6d3ec4,0xbec43f6d,0xbf6d3ec4,
0x3f6dbec4,0xbec43f6d,0x3f6dbec4,0xbec43f6d,0x3ec4bf6d,0x3f6dbec4,0x3ec4bf6d,0x3f6dbec4,0xbf5c3eac,0x3f04bf71,0xbe79bedb,0x3f78bf67,
0xbf2c3f7d,0xbf3e3e16,0xbf803f4e,0xbd49bf18,0x3f183d49,0xbf4e3f80,0xbe163f3e,0xbf7d3f2c,0x3f67bf78,0x3edb3e79,0x3f71bf04,0xbeac3f5c,
0xbf463e95,0x3f22bf75,0x3f22bf75,0x3f46be95,0xbf623f7f,0xbef1bdc9,0xbef1bdc9,0x3f62bf7f,0x3dc93ef1,0xbf7f3f62,0xbf7f3f62,0xbdc9bef1,
0x3f75bf22,0xbe953f46,0xbe953f46,0xbf753f22,0xbf2c3e79,0x3f3ebf78,0x3f80bf5c,0xbd493f04,0xbf7d3f71,0xbe16beac,0x3f18bf67,0x3f4ebedb,
0xbedb3f4e,0xbf673f18,0xbeacbe16,0x3f71bf7d,0x3f04bd49,0xbf5c3f80,0xbf783f3e,0x3e79bf2c,0xbf0e3e48,0x3f55bf7b,0x3f0ebe48,0xbf553f7b,
0xbf7b3f55,0x3e48bf0e,0x3f7bbf55,0xbe483f0e,0xbf553f7b,0xbf0e3e48,0x3f55bf7b,0x3f0ebe48,0xbe483f0e,0xbf7b3f55,0x3e48bf0e,0x3f7bbf55,
0xbedb3e16,0x3f67bf7d,0xbeac3f18,0xbf713f4e,0xbf5c3f2c,0x3f04bf3e,0x3e793d49,0xbf783f80,0xbf803f78,0xbd49be79,0x3f3ebf04,0xbf2c3f5c,
0xbf4e3f71,0xbf183eac,0x3f7dbf67,0xbe163edb,0xbe953dc9,0x3f75bf7f,0xbf753f7f,0xbe953dc9,0xbf223ef1,0x3f46bf62,0xbf463f62,0xbf223ef1,
0xbf623f46,0x3ef1bf22,0xbef13f22,0xbf623f46,0xbf7f3f75,0x3dc9be95,0xbdc93e95,0xbf7f3f75,0xbe163d49,0x3f7dbf80,0xbf4e3f3e,0x3f18bf2c,
0xbeac3e79,0x3f71bf78,0xbf673f5c,0x3edbbf04,0xbf043edb,0x3f5cbf67,0xbf783f71,0x3e79beac,0xbf2c3f18,0x3f3ebf4e,0xbf803f7d,0x3d49be16,
0x3f803f80,0xbf803f80,0x3f803f80,0xbf803f80,0x3f803f80,0xbf803f80,0x3f803f80,0xbf803f80,0x3f803f80,0xbf803f80,0x3f803f80,0xbf803f80,
0x3f803f80,0xbf803f80,0x3f803f80,0xbf803f80,0xbe16bd49,0xbf7dbf80,0xbf4ebf3e,0xbf18bf2c,0xbeacbe79,0xbf71bf78,0xbf67bf5c,0xbedbbf04,
0xbf04bedb,0xbf5cbf67,0xbf78bf71,0xbe79beac,0xbf2cbf18,0xbf3ebf4e,0xbf80bf7d,0xbd49be16,0xbf75bf7f,0x3e953dc9,0x3e953dc9,0x3f753f7f,
0xbf46bf62,0x3f223ef1,0x3f223ef1,0x3f463f62,0xbef1bf22,0x3f623f46,0x3f623f46,0x3ef13f22,0xbdc9be95,0x3f7f3f75,0x3f7f3f75,0x3dc93e95,
0x3edb3e16,0x3f673f7d,0x3eac3f18,0xbf71bf4e,0x3f5c3f2c,0x3f043f3e,0xbe793d49,0xbf78bf80,0x3f803f78,0xbd493e79,0xbf3ebf04,0xbf2cbf5c,
0x3f4e3f71,0xbf18beac,0xbf7dbf67,0xbe16bedb,0x3f553f7b,0xbf0ebe48,0xbf55bf7b,0x3f0e3e48,0x3e483f0e,0xbf7bbf55,0xbe48bf0e,0x3f7b3f55,
0xbf0ebe48,0xbf55bf7b,0x3f0e3e48,0x3f553f7b,0xbf7bbf55,0xbe48bf0e,0x3f7b3f55,0x3e483f0e,0xbf2cbe79,0xbf3ebf78,0x3f803f5c,0x3d493f04,
0xbf7dbf71,0x3e16beac,0x3f183f67,0xbf4ebedb,0xbedbbf4e,0x3f673f18,0xbeac3e16,0xbf71bf7d,0x3f043d49,0x3f5c3f80,0xbf78bf3e,0xbe79bf2c,
0xbf22bf75,0x3f463e95,0xbf46be95,0xbf22bf75,0x3ef1bdc9,0x3f623f7f,0xbf62bf7f,0x3ef1bdc9,0x3f7f3f62,0xbdc93ef1,0x3dc9bef1,0x3f7f3f62,
0x3e953f46,0xbf75bf22,0x3f753f22,0x3e953f46,0x3f5c3eac,0x3f043f71,0x3e79bedb,0x3f783f67,0x3f2c3f7d,0xbf3ebe16,0x3f803f4e,0xbd493f18,
0xbf183d49,0xbf4ebf80,0x3e163f3e,0xbf7dbf2c,0xbf67bf78,0x3edbbe79,0xbf71bf04,0xbeacbf5c,0x3ec43f6d,0xbf6dbec4,0x3ec43f6d,0xbf6dbec4,
0xbf6dbec4,0xbec4bf6d,0xbf6dbec4,0xbec4bf6d,0xbec4bf6d,0x3f6d3ec4,0xbec4bf6d,0x3f6d3ec4,0x3f6d3ec4,0x3ec43f6d,0x3f6d3ec4,0x3ec43f6d,
0xbf78bedb,0xbe79bf67,0xbf5cbf71,0x3f04beac,0xbd49bf4e,0x3f803f18,0x3f2cbe16,0x3f3e3f7d,0x3f7d3f3e,0xbe163f2c,0x3f183f80,0xbf4ebd49,
0xbeac3f04,0xbf71bf5c,0xbf67be79,0xbedbbf78,0xbdc9bf62,0x3f7f3ef1,0x3f7f3ef1,0x3dc93f62,0x3f753f46,0xbe953f22,0xbe953f22,0xbf75bf46,
0xbf223e95,0xbf46bf75,0xbf46bf75,0x3f22be95,0xbef1bf7f,0x3f623dc9,0x3f623dc9,0x3ef13f7f,0x3f803f04,0xbd493f5c,0xbf3e3e79,0xbf2cbf78,
0xbf183edb,0xbf4ebf67,0xbe16bf71,0x3f7d3eac,0xbeacbf7d,0x3f713e16,0x3f673f4e,0xbedb3f18,0x3f783f2c,0xbe793f3e,0xbf5c3d49,0xbf04bf80,
0xbe483f55,0xbf7bbf0e,0x3e48bf55,0x3f7b3f0e,0xbf0ebf7b,0x3f55be48,0x3f0e3f7b,0xbf553e48,0x3f7b3f0e,0xbe483f55,0xbf7bbf0e,0x3e48bf55,
0xbf553e48,0xbf0ebf7b,0x3f55be48,0x3f0e3f7b,0xbf71bf18,0x3eacbf4e,0x3edb3f7d,0xbf673e16,0x3f783d49,0x3e793f80,0xbf5cbf3e,0x3f04bf2c,
0xbf2c3f04,0xbf3ebf5c,0x3f803e79,0x3d493f78,0x3e16bf67,0x3f7d3edb,0xbf4e3eac,0xbf18bf71,0x3ef1bf46,0x3f623f22,0xbf62bf22,0x3ef1bf46,
0xbdc93f75,0xbf7fbe95,0x3f7f3e95,0xbdc93f75,0xbe95bf7f,0x3f75bdc9,0xbf753dc9,0xbe95bf7f,0x3f223f62,0xbf463ef1,0x3f46bef1,0x3f223f62,
0x3f4e3f2c,0xbf183f3e,0x3f7dbd49,0x3e163f80,0xbf67bf04,0x3edbbf5c,0xbf713e79,0xbeacbf78,0x3f783eac,0xbe793f71,0x3f5cbedb,0x3f043f67,
0xbf80be16,0x3d49bf7d,0xbf3e3f18,0xbf2cbf4e,0xbf353f35,0xbf35bf35,0xbf353f35,0xbf35bf35,0x3f35bf35,0x3f353f35,0x3f35bf35,0x3f353f35,
0xbf353f35,0xbf35bf35,0xbf353f35,0xbf35bf35,0x3f35bf35,0x3f353f35,0x3f35bf35,0x3f353f35,0xbf18bf3e,0x3f4ebf2c,0x3e16bf80,0x3f7d3d49,
0x3edb3f5c,0xbf673f04,0xbeac3f78,0xbf71be79,0xbe79bf71,0x3f78beac,0x3f04bf67,0x3f5c3edb,0x3d493f7d,0xbf803e16,0xbf2c3f4e,0xbf3ebf18,
0x3f62bf22,0x3ef13f46,0x3ef13f46,0xbf623f22,0xbf7f3e95,0xbdc9bf75,0xbdc9bf75,0x3f7fbe95,0x3f753dc9,0xbe953f7f,0xbe953f7f,0xbf75bdc9,
0xbf46bef1,0x3f22bf62,0x3f22bf62,0x3f463ef1,0x3eac3f4e,0xbf713f18,0xbf67be16,0x3edbbf7d,0x3e79bf80,0x3f78bd49,0x3f043f2c,0xbf5c3f3e,
0xbf3e3f5c,0xbf2cbf04,0x3d49bf78,0x3f80be79,0x3f7dbedb,0x3e163f67,0xbf183f71,0xbf4ebeac,0xbf7b3f0e,0xbe48bf55,0x3f7bbf0e,0x3e483f55,
0x3f553e48,0xbf0e3f7b,0xbf55be48,0x3f0ebf7b,0xbe48bf55,0x3f7bbf0e,0x3e483f55,0xbf7b3f0e,0xbf0e3f7b,0xbf55be48,0x3f0ebf7b,0x3f553e48,
0xbd49bf5c,0x3f80bf04,0xbf2c3f78,0xbf3ebe79,0xbf4e3f67,0xbf18bedb,0x3f7dbeac,0xbe163f71,0x3f71be16,0xbeac3f7d,0xbedbbf18,0x3f67bf4e,
0xbe79bf3e,0x3f78bf2c,0xbf043f80,0xbf5cbd49,0x3f7fbef1,0xbdc93f62,0x3dc9bf62,0x3f7fbef1,0xbe95bf22,0x3f75bf46,0xbf753f46,0xbe95bf22,
0xbf463f75,0xbf22be95,0x3f223e95,0xbf463f75,0x3f62bdc9,0xbef13f7f,0x3ef1bf7f,0x3f62bdc9,0xbe793f67,0xbf783edb,0x3f043eac,0xbf5c3f71,
0x3f80bf18,0xbd493f4e,0x3f3ebf7d,0x3f2c3e16,0xbe16bf2c,0x3f7dbf3e,0xbf4e3d49,0x3f18bf80,0xbf713f5c,0xbeacbf04,0xbedb3f78,0xbf673e79,
0xbf6d3ec4,0x3ec4bf6d,0xbf6d3ec4,0x3ec4bf6d,0xbec43f6d,0xbf6d3ec4,0xbec43f6d,0xbf6d3ec4,0x3f6dbec4,0xbec43f6d,0x3f6dbec4,0xbec43f6d,
0x3ec4bf6d,0x3f6dbec4,0x3ec4bf6d,0x3f6dbec4,0x3f04bf71,0x3f5cbeac,0x3f78bf67,0x3e793edb,0xbf3e3e16,0x3f2cbf7d,0xbd49bf18,0x3f80bf4e,
0xbf4e3f80,0xbf18bd49,0xbf7d3f2c,0x3e16bf3e,0x3edb3e79,0xbf673f78,0xbeac3f5c,0xbf713f04,0x3f46be95,0xbf223f75,0xbf223f75,0xbf463e95,
0x3f62bf7f,0x3ef13dc9,0x3ef13dc9,0xbf623f7f,0xbdc9bef1,0x3f7fbf62,0x3f7fbf62,0x3dc93ef1,0xbf753f22,0x3e95bf46,0x3e95bf46,0x3f75bf22,
0xbf3e3f78,0xbf2c3e79,0x3d49bf04,0x3f80bf5c,0x3e163eac,0xbf7d3f71,0xbf4e3edb,0x3f18bf67,0x3f67bf18,0xbedb3f4e,0xbf713f7d,0xbeacbe16,
0x3f5cbf80,0x3f04bd49,0xbe793f2c,0xbf783f3e,0xbf0e3e48,0x3f55bf7b,0x3f0ebe48,0xbf553f7b,0xbf7b3f55,0x3e48bf0e,0x3f7bbf55,0xbe483f0e,
0xbf553f7b,0xbf0e3e48,0x3f55bf7b,0x3f0ebe48,0xbe483f0e,0xbf7b3f55,0x3e48bf0e,0x3f7bbf55,0x3f67bf7d,0x3edbbe16,0xbf713f4e,0x3eacbf18,
0x3f04bf3e,0x3f5cbf2c,0xbf783f80,0xbe79bd49,0xbd49be79,0x3f80bf78,0xbf2c3f5c,0xbf3e3f04,0xbf183eac,0x3f4ebf71,0xbe163edb,0xbf7d3f67,
0x3e95bdc9,0xbf753f7f,0x3f75bf7f,0x3e95bdc9,0x3f22bef1,0xbf463f62,0x3f46bf62,0x3f22bef1,0x3f62bf46,0xbef13f22,0x3ef1bf22,0x3f62bf46,
0x3f7fbf75,0xbdc93e95,0x3dc9be95,0x3f7fbf75,0xbf7d3f80,0xbe163d49,0xbf183f2c,0xbf4e3f3e,0xbf713f78,0xbeac3e79,0xbedb3f04,0xbf673f5c,
0xbf5c3f67,0xbf043edb,0xbe793eac,0xbf783f71,0xbf3e3f4e,0xbf2c3f18,0xbd493e16,0xbf803f7d,0x3f803f80,0xbf803f80,0x3f803f80,0xbf803f80,
0x3f803f80,0xbf803f80,0x3f803f80,0xbf803f80,0x3f803f80,0xbf803f80,0x3f803f80,0xbf803f80,0x3f803f80,0xbf803f80,0x3f803f80,0xbf803f80,
0xbf7dbf80,0x3e163d49,0xbf18bf2c,0x3f4e3f3e,0xbf71bf78,0x3eac3e79,0xbedbbf04,0x3f673f5c,0xbf5cbf67,0x3f043edb,0xbe79beac,0x3f783f71,
0xbf3ebf4e,0x3f2c3f18,0xbd49be16,0x3f803f7d,0x3f753f7f,0xbe95bdc9,0xbe95bdc9,0xbf75bf7f,0x3f463f62,0xbf22bef1,0xbf22bef1,0xbf46bf62,
0x3ef13f22,0xbf62bf46,0xbf62bf46,0xbef1bf22,0x3dc93e95,0xbf7fbf75,0xbf7fbf75,0xbdc9be95,0xbf67bf7d,0x3edb3e16,0x3f713f4e,0x3eac3f18,
0xbf04bf3e,0x3f5c3f2c,0x3f783f80,0xbe793d49,0x3d49be79,0x3f803f78,0x3f2c3f5c,0xbf3ebf04,0x3f183eac,0x3f4e3f71,0x3e163edb,0xbf7dbf67,
0x3f553f7b,0xbf0ebe48,0xbf55bf7b,0x3f0e3e48,0x3e483f0e,0xbf7bbf55,0xbe48bf0e,0x3f7b3f55,0xbf0ebe48,0xbf55bf7b,0x3f0e3e48,0x3f553f7b,
0xbf7bbf55,0xbe48bf0e,0x3f7b3f55,0x3e483f0e,0xbf3ebf78,0x3f2c3e79,0x3d493f04,0xbf80bf5c,0x3e16beac,0x3f7d3f71,0xbf4ebedb,0xbf18bf67,
0x3f673f18,0x3edb3f4e,0xbf71bf7d,0x3eacbe16,0x3f5c3f80,0xbf04bd49,0xbe79bf2c,0x3f783f3e,0x3f223f75,0xbf46be95,0x3f463e95,0x3f223f75,
0xbef13dc9,0xbf62bf7f,0x3f623f7f,0xbef13dc9,0xbf7fbf62,0x3dc9bef1,0xbdc93ef1,0xbf7fbf62,0xbe95bf46,0x3f753f22,0xbf75bf22,0xbe95bf46,
0xbf04bf71,0x3f5c3eac,0xbf78bf67,0x3e79bedb,0x3f3e3e16,0x3f2c3f7d,0x3d49bf18,0x3f803f4e,0x3f4e3f80,0xbf183d49,0x3f7d3f2c,0x3e163f3e,
0xbedb3e79,0xbf67bf78,0x3eac3f5c,0xbf71bf04,0x3ec43f6d,0xbf6dbec4,0x3ec43f6d,0xbf6dbec4,0xbf6dbec4,0xbec4bf6d,0xbf6dbec4,0xbec4bf6d,
0xbec4bf6d,0x3f6d3ec4,0xbec4bf6d,0x3f6d3ec4,0x3f6d3ec4,0x3ec43f6d,0x3f6d3ec4,0x3ec43f6d,0xbe79bf67,0x3f783edb,0x3f04beac,0x3f5c3f71,
0x3f803f18,0x3d493f4e,0x3f3e3f7d,0xbf2c3e16,0xbe163f2c,0xbf7dbf3e,0xbf4ebd49,0xbf18bf80,0xbf71bf5c,0x3eacbf04,0xbedbbf78,0x3f673e79,
0x3dc93f62,0xbf7fbef1,0xbf7fbef1,0xbdc9bf62,0xbf75bf46,0x3e95bf22,0x3e95bf22,0x3f753f46,0x3f22be95,0x3f463f75,0x3f463f75,0xbf223e95,
0x3ef13f7f,0xbf62bdc9,0xbf62bdc9,0xbef1bf7f,0x3d49bf5c,0x3f803f04,0x3f2c3f78,0xbf3e3e79,0x3f4e3f67,0xbf183edb,0xbf7dbeac,0xbe16bf71,
0xbf71be16,0xbeacbf7d,0x3edbbf18,0x3f673f4e,0x3e79bf3e,0x3f783f2c,0x3f043f80,0xbf5c3d49,0xbe483f55,0xbf7bbf0e,0x3e48bf55,0x3f7b3f0e,
0xbf0ebf7b,0x3f55be48,0x3f0e3f7b,0xbf553e48,0x3f7b3f0e,0xbe483f55,0xbf7bbf0e,0x3e48bf55,0xbf553e48,0xbf0ebf7b,0x3f55be48,0x3f0e3f7b,
0x3eacbf4e,0x3f713f18,0xbf673e16,0xbedbbf7d,0x3e793f80,0xbf78bd49,0x3f04bf2c,0x3f5c3f3e,0xbf3ebf5c,0x3f2cbf04,0x3d493f78,0xbf80be79,
0x3f7d3edb,0xbe163f67,0xbf18bf71,0x3f4ebeac,0xbef13f46,0xbf62bf22,0x3f623f22,0xbef13f46,0x3dc9bf75,0x3f7f3e95,0xbf7fbe95,0x3dc9bf75,
0x3e953f7f,0xbf753dc9,0x3f75bdc9,0x3e953f7f,0xbf22bf62,0x3f46bef1,0xbf463ef1,0xbf22bf62,0x3f18bf3e,0x3f4e3f2c,0xbe16bf80,0x3f7dbd49,
0xbedb3f5c,0xbf67bf04,0x3eac3f78,0xbf713e79,0x3e79bf71,0x3f783eac,0xbf04bf67,0x3f5cbedb,0xbd493f7d,0xbf80be16,0x3f2c3f4e,0xbf3e3f18,
0xbf353f35,0xbf35bf35,0xbf353f35,0xbf35bf35,0x3f35bf35,0x3f353f35,0x3f35bf35,0x3f353f35,0xbf353f35,0xbf35bf35,0xbf353f35,0xbf35bf35,
0x3f35bf35,0x3f353f35,0x3f35bf35,0x3f353f35,0x3f4ebf2c,0x3f183f3e,0x3f7d3d49,0xbe163f80,0xbf673f04,0xbedbbf5c,0xbf71be79,0x3eacbf78,
0x3f78beac,0x3e793f71,0x3f5c3edb,0xbf043f67,0xbf803e16,0xbd49bf7d,0xbf3ebf18,0x3f2cbf4e,0xbf623f22,0xbef1bf46,0xbef1bf46,0x3f62bf22,
0x3f7fbe95,0x3dc93f75,0x3dc93f75,0xbf7f3e95,0xbf75bdc9,0x3e95bf7f,0x3e95bf7f,0x3f753dc9,0x3f463ef1,0xbf223f62,0xbf223f62,0xbf46bef1,
0x3f71bf18,0x3eac3f4e,0xbedb3f7d,0xbf67be16,0xbf783d49,0x3e79bf80,0x3f5cbf3e,0x3f043f2c,0x3f2c3f04,0xbf3e3f5c,0xbf803e79,0x3d49bf78,
0xbe16bf67,0x3f7dbedb,0x3f4e3eac,0xbf183f71,0xbf7b3f0e,0xbe48bf55,0x3f7bbf0e,0x3e483f55,0x3f553e48,0xbf0e3f7b,0xbf55be48,0x3f0ebf7b,
0xbe48bf55,0x3f7bbf0e,0x3e483f55,0xbf7b3f0e,0xbf0e3f7b,0xbf55be48,0x3f0ebf7b,0x3f553e48,0x3f80bf04,0x3d493f5c,0xbf3ebe79,0x3f2cbf78,
0xbf18bedb,0x3f4ebf67,0xbe163f71,0xbf7d3eac,0xbeac3f7d,0xbf713e16,0x3f67bf4e,0x3edb3f18,0x3f78bf2c,0x3e793f3e,0xbf5cbd49,0x3f04bf80,
0xbf7f3ef1,0x3dc9bf62,0xbdc93f62,0xbf7f3ef1,0x3e953f22,0xbf753f46,0x3f75bf46,0x3e953f22,0x3f46bf75,0x3f223e95,0xbf22be95,0x3f46bf75,
0xbf623dc9,0x3ef1bf7f,0xbef13f7f,0xbf623dc9,0x3f78bedb,0xbe793f67,0x3f5cbf71,0x3f043eac,0x3d49bf4e,0x3f80bf18,0xbf2cbe16,0x3f3ebf7d,
0xbf7d3f3e,0xbe16bf2c,0xbf183f80,0xbf4e3d49,0x3eac3f04,0xbf713f5c,0x3f67be79,0xbedb3f78,0xbf6d3ec4,0x3ec4bf6d,0xbf6d3ec4,0x3ec4bf6d,
0xbec43f6d,0xbf6d3ec4,0xbec43f6d,0xbf6d3ec4,0x3f6dbec4,0xbec43f6d,0x3f6dbec4,0xbec43f6d,0x3ec4bf6d,0x3f6dbec4,0x3ec4bf6d,0x3f6dbec4,
0x3f5cbeac,0xbf043f71,0x3e793edb,0xbf783f67,0x3f2cbf7d,0x3f3ebe16,0x3f80bf4e,0x3d493f18,0xbf18bd49,0x3f4ebf80,0x3e16bf3e,0x3f7dbf2c,
0xbf673f78,0xbedbbe79,0xbf713f04,0x3eacbf5c,0xbf463e95,0x3f22bf75,0x3f22bf75,0x3f46be95,0xbf623f7f,0xbef1bdc9,0xbef1bdc9,0x3f62bf7f,
0x3dc93ef1,0xbf7f3f62,0xbf7f3f62,0xbdc9bef1,0x3f75bf22,0xbe953f46,0xbe953f46,0xbf753f22,0x3f2cbe79,0xbf3e3f78,0xbf803f5c,0x3d49bf04,
0x3f7dbf71,0x3e163eac,0xbf183f67,0xbf4e3edb,0x3edbbf4e,0x3f67bf18,0x3eac3e16,0xbf713f7d,0xbf043d49,0x3f5cbf80,0x3f78bf3e,0xbe793f2c,
0xbf0e3e48,0x3f55bf7b,0x3f0ebe48,0xbf553f7b,0xbf7b3f55,0x3e48bf0e,0x3f7bbf55,0xbe483f0e,0xbf553f7b,0xbf0e3e48,0x3f55bf7b,0x3f0ebe48,
0xbe483f0e,0xbf7b3f55,0x3e48bf0e,0x3f7bbf55,0x3edbbe16,0xbf673f7d,0x3eacbf18,0x3f71bf4e,0x3f5cbf2c,0xbf043f3e,0xbe79bd49,0x3f78bf80,
0x3f80bf78,0x3d493e79,0xbf3e3f04,0x3f2cbf5c,0x3f4ebf71,0x3f18beac,0xbf7d3f67,0x3e16bedb,0xbe953dc9,0x3f75bf7f,0xbf753f7f,0xbe953dc9,
0xbf223ef1,0x3f46bf62,0xbf463f62,0xbf223ef1,0xbf623f46,0x3ef1bf22,0xbef13f22,0xbf623f46,0xbf7f3f75,0x3dc9be95,0xbdc93e95,0xbf7f3f75,
0x3e16bd49,0xbf7d3f80,0x3f4ebf3e,0xbf183f2c,0x3eacbe79,0xbf713f78,0x3f67bf5c,0xbedb3f04,0x3f04bedb,0xbf5c3f67,0x3f78bf71,0xbe793eac,
0x3f2cbf18,0xbf3e3f4e,0x3f80bf7d,0xbd493e16,0x3f803f80,0xbf803f80,0x3f803f80,0xbf803f80,0x3f803f80,0xbf803f80,0x3f803f80,0xbf803f80,
0x3f803f80,0xbf803f80,0x3f803f80,0xbf803f80,0x3f803f80,0xbf803f80,0x3f803f80,0xbf803f80,0x3e163d49,0x3f7d3f80,0x3f4e3f3e,0x3f183f2c,
0x3eac3e79,0x3f713f78,0x3f673f5c,0x3edb3f04,0x3f043edb,0x3f5c3f67,0x3f783f71,0x3e793eac,0x3f2c3f18,0x3f3e3f4e,0x3f803f7d,0x3d493e16,
0xbf75bf7f,0x3e953dc9,0x3e953dc9,0x3f753f7f,0xbf46bf62,0x3f223ef1,0x3f223ef1,0x3f463f62,0xbef1bf22,0x3f623f46,0x3f623f46,0x3ef13f22,
0xbdc9be95,0x3f7f3f75,0x3f7f3f75,0x3dc93e95,0xbedbbe16,0xbf67bf7d,0xbeacbf18,0x3f713f4e,0xbf5cbf2c,0xbf04bf3e,0x3e79bd49,0x3f783f80,
0xbf80bf78,0x3d49be79,0x3f3e3f04,0x3f2c3f5c,0xbf4ebf71,0x3f183eac,0x3f7d3f67,0x3e163edb,0x3f553f7b,0xbf0ebe48,0xbf55bf7b,0x3f0e3e48,
0x3e483f0e,0xbf7bbf55,0xbe48bf0e,0x3f7b3f55,0xbf0ebe48,0xbf55bf7b,0x3f0e3e48,0x3f553f7b,0xbf7bbf55,0xbe48bf0e,0x3f7b3f55,0x3e483f0e,
0x3f2c3e79,0x3f3e3f78,0xbf80bf5c,0xbd49bf04,0x3f7d3f71,0xbe163eac,0xbf18bf67,0x3f4e3edb,0x3edb3f4e,0xbf67bf18,0x3eacbe16,0x3f713f7d,
0xbf04bd49,0xbf5cbf80,0x3f783f3e,0x3e793f2c,0xbf22bf75,0x3f463e95,0xbf46be95,0xbf22bf75,0x3ef1bdc9,0x3f623f7f,0xbf62bf7f,0x3ef1bdc9,
0x3f7f3f62,0xbdc93ef1,0x3dc9bef1,0x3f7f3f62,0x3e953f46,0xbf75bf22,0x3f753f22,0x3e953f46,0xbf5cbeac,0xbf04bf71,0xbe793edb,0xbf78bf67,
0xbf2cbf7d,0x3f3e3e16,0xbf80bf4e,0x3d49bf18,0x3f18bd49,0x3f4e3f80,0xbe16bf3e,0x3f7d3f2c,0x3f673f78,0xbedb3e79,0x3f713f04,0x3eac3f5c,
0x3ec43f6d,0xbf6dbec4,0x3ec43f6d,0xbf6dbec4,0xbf6dbec4,0xbec4bf6d,0xbf6dbec4,0xbec4bf6d,0xbec4bf6d,0x3f6d3ec4,0xbec4bf6d,0x3f6d3ec4,
0x3f6d3ec4,0x3ec43f6d,0x3f6d3ec4,0x3ec43f6d,0x3f783edb,0x3e793f67,0x3f5c3f71,0xbf043eac,0x3d493f4e,0xbf80bf18,0xbf2c3e16,0xbf3ebf7d,
0xbf7dbf3e,0x3e16bf2c,0xbf18bf80,0x3f4e3d49,0x3eacbf04,0x3f713f5c,0x3f673e79,0x3edb3f78,0xbdc9bf62,0x3f7f3ef1,0x3f7f3ef1,0x3dc93f62,
0x3f753f46,0xbe953f22,0xbe953f22,0xbf75bf46,0xbf223e95,0xbf46bf75,0xbf46bf75,0x3f22be95,0xbef1bf7f,0x3f623dc9,0x3f623dc9,0x3ef13f7f,
0xbf80bf04,0x3d49bf5c,0x3f3ebe79,0x3f2c3f78,0x3f18bedb,0x3f4e3f67,0x3e163f71,0xbf7dbeac,0x3eac3f7d,0xbf71be16,0xbf67bf4e,0x3edbbf18,
0xbf78bf2c,0x3e79bf3e,0x3f5cbd49,0x3f043f80,0xbe483f55,0xbf7bbf0e,0x3e48bf55,0x3f7b3f0e,0xbf0ebf7b,0x3f55be48,0x3f0e3f7b,0xbf553e48,
0x3f7b3f0e,0xbe483f55,0xbf7bbf0e,0x3e48bf55,0xbf553e48,0xbf0ebf7b,0x3f55be48,0x3f0e3f7b,0x3f713f18,0xbeac3f4e,0xbedbbf7d,0x3f67be16,
0xbf78bd49,0xbe79bf80,0x3f5c3f3e,0xbf043f2c,0x3f2cbf04,0x3f3e3f5c,0xbf80be79,0xbd49bf78,0xbe163f67,0xbf7dbedb,0x3f4ebeac,0x3f183f71,
0x3ef1bf46,0x3f623f22,0xbf62bf22,0x3ef1bf46,0xbdc93f75,0xbf7fbe95,0x3f7f3e95,0xbdc93f75,0xbe95bf7f,0x3f75bdc9,0xbf753dc9,0xbe95bf7f,
0x3f223f62,0xbf463ef1,0x3f46bef1,0x3f223f62,0xbf4ebf2c,0x3f18bf3e,0xbf7d3d49,0xbe16bf80,0x3f673f04,0xbedb3f5c,0x3f71be79,0x3eac3f78,
0xbf78beac,0x3e79bf71,0xbf5c3edb,0xbf04bf67,0x3f803e16,0xbd493f7d,0x3f3ebf18,0x3f2c3f4e,0xbf353f35,0xbf35bf35,0xbf353f35,0xbf35bf35,
0x3f35bf35,0x3f353f35,0x3f35bf35,0x3f353f35,0xbf353f35,0xbf35bf35,0xbf353f35,0xbf35bf35,0x3f35bf35,0x3f353f35,0x3f35bf35,0x3f353f35,
0x3f183f3e,0xbf4e3f2c,0xbe163f80,0xbf7dbd49,0xbedbbf5c,0x3f67bf04,0x3eacbf78,0x3f713e79,0x3e793f71,0xbf783eac,0xbf043f67,0xbf5cbedb,
0xbd49bf7d,0x3f80be16,0x3f2cbf4e,0x3f3e3f18,0x3f62bf22,0x3ef13f46,0x3ef13f46,0xbf623f22,0xbf7f3e95,0xbdc9bf75,0xbdc9bf75,0x3f7fbe95,
0x3f753dc9,0xbe953f7f,0xbe953f7f,0xbf75bdc9,0xbf46bef1,0x3f22bf62,0x3f22bf62,0x3f463ef1,0xbeacbf4e,0x3f71bf18,0x3f673e16,0xbedb3f7d,
0xbe793f80,0xbf783d49,0xbf04bf2c,0x3f5cbf3e,0x3f3ebf5c,0x3f2c3f04,0xbd493f78,0xbf803e79,0xbf7d3edb,0xbe16bf67,0x3f18bf71,0x3f4e3eac,
0xbf7b3f0e,0xbe48bf55,0x3f7bbf0e,0x3e483f55,0x3f553e48,0xbf0e3f7b,0xbf55be48,0x3f0ebf7b,0xbe48bf55,0x3f7bbf0e,0x3e483f55,0xbf7b3f0e,
0xbf0e3f7b,0xbf55be48,0x3f0ebf7b,0x3f553e48,0x3d493f5c,0xbf803f04,0x3f2cbf78,0x3f3e3e79,0x3f4ebf67,0x3f183edb,0xbf7d3eac,0x3e16bf71,
0xbf713e16,0x3eacbf7d,0x3edb3f18,0xbf673f4e,0x3e793f3e,0xbf783f2c,0x3f04bf80,0x3f5c3d49,0x3f7fbef1,0xbdc93f62,0x3dc9bf62,0x3f7fbef1,
0xbe95bf22,0x3f75bf46,0xbf753f46,0xbe95bf22,0xbf463f75,0xbf22be95,0x3f223e95,0xbf463f75,0x3f62bdc9,0xbef13f7f,0x3ef1bf7f,0x3f62bdc9,
0x3e79bf67,0x3f78bedb,0xbf04beac,0x3f5cbf71,0xbf803f18,0x3d49bf4e,0xbf3e3f7d,0xbf2cbe16,0x3e163f2c,0xbf7d3f3e,0x3f4ebd49,0xbf183f80,
0x3f71bf5c,0x3eac3f04,0x3edbbf78,0x3f67be79,0xbf6d3ec4,0x3ec4bf6d,0xbf6d3ec4,0x3ec4bf6d,0xbec43f6d,0xbf6d3ec4,0xbec43f6d,0xbf6d3ec4,
0x3f6dbec4,0xbec43f6d,0x3f6dbec4,0xbec43f6d,0x3ec4bf6d,0x3f6dbec4,0x3ec4bf6d,0x3f6dbec4,0xbf043f71,0xbf5c3eac,0xbf783f67,0xbe79bedb,
0x3f3ebe16,0xbf2c3f7d,0x3d493f18,0xbf803f4e,0x3f4ebf80,0x3f183d49,0x3f7dbf2c,0xbe163f3e,0xbedbbe79,0x3f67bf78,0x3eacbf5c,0x3f71bf04,
0x3f46be95,0xbf223f75,0xbf223f75,0xbf463e95,0x3f62bf7f,0x3ef13dc9,0x3ef13dc9,0xbf623f7f,0xbdc9bef1,0x3f7fbf62,0x3f7fbf62,0x3dc93ef1,
0xbf753f22,0x3e95bf46,0x3e95bf46,0x3f75bf22,0x3f3ebf78,0x3f2cbe79,0xbd493f04,0xbf803f5c,0xbe16beac,0x3f7dbf71,0x3f4ebedb,0xbf183f67,
0xbf673f18,0x3edbbf4e,0x3f71bf7d,0x3eac3e16,0xbf5c3f80,0xbf043d49,0x3e79bf2c,0x3f78bf3e,0xbf0e3e48,0x3f55bf7b,0x3f0ebe48,0xbf553f7b,
0xbf7b3f55,0x3e48bf0e,0x3f7bbf55,0xbe483f0e,0xbf553f7b,0xbf0e3e48,0x3f55bf7b,0x3f0ebe48,0xbe483f0e,0xbf7b3f55,0x3e48bf0e,0x3f7bbf55,
0xbf673f7d,0xbedb3e16,0x3f71bf4e,0xbeac3f18,0xbf043f3e,0xbf5c3f2c,0x3f78bf80,0x3e793d49,0x3d493e79,0xbf803f78,0x3f2cbf5c,0x3f3ebf04,
0x3f18beac,0xbf4e3f71,0x3e16bedb,0x3f7dbf67,0x3e95bdc9,0xbf753f7f,0x3f75bf7f,0x3e95bdc9,0x3f22bef1,0xbf463f62,0x3f46bf62,0x3f22bef1,
0x3f62bf46,0xbef13f22,0x3ef1bf22,0x3f62bf46,0x3f7fbf75,0xbdc93e95,0x3dc9be95,0x3f7fbf75,0x3f7dbf80,0x3e16bd49,0x3f18bf2c,0x3f4ebf3e,
0x3f71bf78,0x3eacbe79,0x3edbbf04,0x3f67bf5c,0x3f5cbf67,0x3f04bedb,0x3e79beac,0x3f78bf71,0x3f3ebf4e,0x3f2cbf18,0x3d49be16,0x3f80bf7d,
0x3f803f80,0xbf353f35,0x3f803f80,0xbf353f35,0x3f803f80,0xbf353f35,0x3f803f80,0xbf353f35,0x3f803f80,0xbf353f35,0x3f803f80,0xbf353f35,
0x3f803f80,0xbf353f35,0x3f803f80,0xbf353f35,0x3f7c3f7f,0xbe2fbd97,0x3f133f27,0xbf51bf42,0x3f6f3f77,0xbeb8be89,0x3ecf3efc,0xbf6abf5f,
0x3f583f65,0xbf09bee6,0x3e603ea1,0xbf7abf73,0x3f393f4a,0xbf31bf1d,0x3cc93dfb,0xbf80bf7e,0x3f713f7d,0xbeacbe16,0xbeacbe16,0xbf71bf7d,
0x3f3e3f5c,0xbf2cbf04,0xbf2cbf04,0xbf3ebf5c,0x3edb3f18,0xbf67bf4e,0xbf67bf4e,0xbedbbf18,0x3d493e79,0xbf80bf78,0xbf80bf78,0xbd49be79,
0x3f5f3f7a,0xbefcbe60,0xbf77bf58,0xbe89bf09,0x3ee63f31,0xbf65bf39,0xbf73bf80,0x3ea13cc9,0xbdfb3e2f,0xbf7ebf7c,0xbf1dbf51,0x3f4a3f13,
0xbf27becf,0xbf42bf6a,0xbd97beb8,0x3f7f3f6f,0x3f463f75,0xbf22be95,0xbf46bf75,0x3f223e95,0x3dc93ef1,0xbf7fbf62,0xbdc9bef1,0x3f7f3f62,
0xbf22be95,0xbf46bf75,0x3f223e95,0x3f463f75,0xbf7fbf62,0xbdc9bef1,0x3f7f3f62,0x3dc93ef1,0x3f273f6f,0xbf42beb8,0x3d97becf,0x3f7f3f6a,
0xbe893e60,0xbf77bf7a,0x3f5f3f09,0x3efc3f58,0xbf73bf31,0xbea1bf39,0x3f653f80,0xbee63cc9,0xbf4abf7c,0x3f1d3e2f,0x3dfb3f13,0xbf7ebf51,
0x3f043f67,0xbf5cbedb,0x3f5c3edb,0x3f043f67,0xbf18bd49,0xbf4ebf80,0x3f4e3f80,0xbf18bd49,0xbf78bf71,0x3e79beac,0xbe793eac,0xbf78bf71,
0xbe16bf2c,0x3f7d3f3e,0xbf7dbf3e,0xbe16bf2c,0x3eb83f5f,0xbf6fbefc,0x3f6a3f77,0xbecf3e89,0xbf58bea1,0xbf09bf73,0xbe603ee6,0xbf7abf65,
0xbf31bf7e,0x3f393dfb,0xbf80bf4a,0x3cc9bf1d,0x3f13bd97,0x3f513f7f,0xbe2fbf42,0x3f7c3f27,0x3e483f55,0xbf7bbf0e,0x3e483f55,0xbf7bbf0e,
0xbf7bbf0e,0xbe48bf55,0xbf7bbf0e,0xbe48bf55,0xbe48bf55,0x3f7b3f0e,0xbe48bf55,0x3f7b3f0e,0x3f7b3f0e,0x3e483f55,0x3f7b3f0e,0x3e483f55,
0x3cc93f4a,0xbf80bf1d,0xbf313dfb,0xbf39bf7e,0xbf7cbf42,0x3e2fbf27,0xbf13bf7f,0x3f513d97,0x3eb8befc,0x3f6f3f5f,0x3f6a3e89,0x3ecf3f77,
0x3f583f73,0xbf093ea1,0x3e603f65,0xbf7abee6,0xbe163f3e,0xbf7dbf2c,0xbf7dbf2c,0x3e16bf3e,0xbf5cbf67,0x3f04bedb,0x3f04bedb,0x3f5c3f67,
0x3f4ebd49,0x3f183f80,0x3f183f80,0xbf4e3d49,0x3e793f71,0xbf78beac,0xbf78beac,0xbe79bf71,0xbea13f31,0xbf73bf39,0xbee6bf80,0x3f653cc9,
0xbf1dbf7c,0x3f4abe2f,0x3f7e3f13,0xbdfb3f51,0x3f7f3ecf,0x3d973f6a,0xbf273eb8,0xbf42bf6f,0xbefc3f09,0xbf5fbf58,0xbe89bf7a,0x3f773e60,
0xbef13f22,0xbf62bf46,0x3ef1bf22,0x3f623f46,0xbe95bf7f,0x3f753dc9,0x3e953f7f,0xbf75bdc9,0x3f623f46,0xbef13f22,0xbf62bf46,0x3ef1bf22,
0xbf75bdc9,0xbe95bf7f,0x3f753dc9,0x3e953f7f,0xbf1d3f13,0xbf4abf51,0x3f7e3e2f,0x3dfb3f7c,0x3d97bf6f,0x3f7f3eb8,0xbf423ecf,0xbf27bf6a,
0x3efc3f7a,0xbf5f3e60,0x3e89bf58,0x3f773f09,0xbf65bf31,0x3ee6bf39,0x3ea13f80,0xbf733cc9,0xbf3e3f04,0xbf2cbf5c,0x3f2c3f5c,0xbf3e3f04,
0x3edbbf4e,0x3f673f18,0xbf67bf18,0x3edbbf4e,0xbd493f78,0xbf80be79,0x3f803e79,0xbd493f78,0xbeacbf7d,0x3f71be16,0xbf713e16,0xbeacbf7d,
0xbf583ee6,0xbf09bf65,0xbe603f73,0xbf7abea1,0x3f39bf1d,0x3f313f4a,0x3cc9bf7e,0x3f803dfb,0xbf133f42,0xbf51bf27,0x3e2f3f7f,0xbf7c3d97,
0x3ecfbf5f,0x3f6a3efc,0xbeb8bf77,0x3f6fbe89,0xbf6d3ec4,0xbec4bf6d,0xbf6d3ec4,0xbec4bf6d,0x3f6dbec4,0x3ec43f6d,0x3f6dbec4,0x3ec43f6d,
0xbf6d3ec4,0xbec4bf6d,0xbf6d3ec4,0xbec4bf6d,0x3f6dbec4,0x3ec43f6d,0x3f6dbec4,0x3ec43f6d,0xbf7a3ea1,0xbe60bf73,0xbf58bee6,0x3f09bf65,
0x3f80bdfb,0x3cc93f7e,0x3f393f1d,0xbf313f4a,0xbf7cbd97,0x3e2fbf7f,0xbf13bf42,0x3f51bf27,0x3f6f3e89,0xbeb83f77,0x3ecf3f5f,0xbf6a3efc,
0xbf803e79,0xbd49bf78,0xbd49bf78,0x3f80be79,0x3f713e16,0xbeac3f7d,0xbeac3f7d,0xbf71be16,0xbf3ebf04,0x3f2cbf5c,0x3f2cbf5c,0x3f3e3f04,
0x3edb3f4e,0xbf673f18,0xbf673f18,0xbedbbf4e,0xbf7e3e2f,0x3dfbbf7c,0x3f4abf51,0x3f1d3f13,0x3f423ecf,0xbf273f6a,0xbf7f3eb8,0xbd97bf6f,
0xbe89bf58,0x3f77bf09,0x3f5f3e60,0xbefc3f7a,0xbea13f80,0xbf73bcc9,0xbee6bf39,0x3f65bf31,0xbf753dc9,0x3e95bf7f,0x3f75bdc9,0xbe953f7f,
0x3ef13f22,0xbf623f46,0xbef1bf22,0x3f62bf46,0x3e95bf7f,0x3f75bdc9,0xbe953f7f,0xbf753dc9,0xbf623f46,0xbef1bf22,0x3f62bf46,0x3ef13f22,
0xbf653cc9,0x3ee6bf80,0x3ea13f31,0xbf733f39,0x3dfb3f51,0xbf7e3f13,0x3f1dbf7c,0x3f4a3e2f,0x3f42bf6f,0x3f273eb8,0xbf7f3ecf,0x3d97bf6a,
0xbf773e60,0x3e89bf7a,0x3efc3f09,0xbf5f3f58,0xbf4ebd49,0x3f18bf80,0xbf183f80,0xbf4ebd49,0xbe793f71,0xbf783eac,0x3f78beac,0xbe793f71,
0x3f7dbf2c,0x3e163f3e,0xbe16bf3e,0x3f7dbf2c,0xbf04bedb,0x3f5cbf67,0xbf5c3f67,0xbf04bedb,0xbf31bdfb,0x3f39bf7e,0xbf803f1d,0x3cc9bf4a,
0xbf133f7f,0xbf513d97,0x3e2f3f27,0xbf7c3f42,0x3f6abe89,0xbecf3f77,0x3f6fbf5f,0x3eb83efc,0x3e60bf65,0x3f7abee6,0xbf09bea1,0x3f58bf73,
0xbf0ebe48,0x3f55bf7b,0xbf0ebe48,0x3f55bf7b,0xbf553f7b,0xbf0ebe48,0xbf553f7b,0xbf0ebe48,0x3f0e3e48,0xbf553f7b,0x3f0e3e48,0xbf553f7b,
0x3f55bf7b,0x3f0e3e48,0x3f55bf7b,0x3f0e3e48,0xbecfbe89,0x3f6abf77,0x3eb8bf5f,0x3f6fbefc,0xbf7a3f65,0xbe60bee6,0xbf583ea1,0x3f09bf73,
0x3cc93f1d,0xbf803f4a,0xbf313f7e,0xbf393dfb,0x3f7cbf27,0xbe2f3f42,0x3f133d97,0xbf513f7f,0xbe79beac,0x3f78bf71,0x3f78bf71,0x3e793eac,
0xbf7d3f3e,0x3e16bf2c,0x3e16bf2c,0x3f7dbf3e,0xbf043f67,0xbf5c3edb,0xbf5c3edb,0x3f04bf67,0x3f18bd49,0xbf4e3f80,0xbf4e3f80,0xbf183d49,
0xbd97becf,0x3f7fbf6a,0x3f42beb8,0xbf273f6f,0xbf5f3f09,0x3efcbf58,0x3f77bf7a,0x3e893e60,0xbf653f80,0xbee6bcc9,0x3ea1bf39,0x3f73bf31,
0xbdfb3f13,0xbf7e3f51,0xbf1d3e2f,0x3f4abf7c,0x3dc9bef1,0x3f7fbf62,0xbdc93ef1,0xbf7f3f62,0xbf223e95,0x3f46bf75,0x3f22be95,0xbf463f75,
0xbf7f3f62,0x3dc9bef1,0x3f7fbf62,0xbdc93ef1,0xbf463f75,0xbf223e95,0x3f46bf75,0x3f22be95,0x3e89bf09,0x3f77bf58,0xbf5f3f7a,0xbefc3e60,
0xbea13cc9,0x3f73bf80,0xbee63f31,0xbf653f39,0xbf4a3f13,0x3f1dbf51,0x3dfb3e2f,0xbf7e3f7c,0xbf7f3f6f,0x3d97beb8,0x3f27becf,0xbf423f6a,
0x3edbbf18,0x3f67bf4e,0xbf673f4e,0x3edbbf18,0x3d49be79,0x3f80bf78,0xbf803f78,0x3d49be79,0xbeac3e16,0x3f71bf7d,0xbf713f7d,0xbeac3e16,
0xbf2c3f04,0x3f3ebf5c,0xbf3e3f5c,0xbf2c3f04,0x3f13bf27,0x3f51bf42,0xbe2f3d97,0x3f7cbf7f,0x3ecfbefc,0x3f6abf5f,0xbeb83e89,0x3f6fbf77,
0x3e60bea1,0x3f7abf73,0xbf093ee6,0x3f58bf65,0x3cc9bdfb,0x3f80bf7e,0xbf313f1d,0x3f39bf4a,0x3f803f80,0xbf353f35,0x3f803f80,0xbf353f35,
0x3f803f80,0xbf353f35,0x3f803f80,0xbf353f35,0x3f803f80,0xbf353f35,0x3f803f80,0xbf353f35,0x3f803f80,0xbf353f35,0x3f803f80,0xbf353f35,
0xbe2fbd97,0xbf7cbf7f,0xbf51bf42,0xbf13bf27,0xbeb8be89,0xbf6fbf77,0xbf6abf5f,0xbecfbefc,0xbf09bee6,0xbf58bf65,0xbf7abf73,0xbe60bea1,
0xbf31bf1d,0xbf39bf4a,0xbf80bf7e,0xbcc9bdfb,0xbf71bf7d,0x3eac3e16,0x3eac3e16,0x3f713f7d,0xbf3ebf5c,0x3f2c3f04,0x3f2c3f04,0x3f3e3f5c,
0xbedbbf18,0x3f673f4e,0x3f673f4e,0x3edb3f18,0xbd49be79,0x3f803f78,0x3f803f78,0x3d493e79,0x3efc3e60,0x3f5f3f7a,0x3e893f09,0xbf77bf58,
0x3f653f39,0x3ee63f31,0xbea1bcc9,0xbf73bf80,0x3f7e3f7c,0xbdfb3e2f,0xbf4abf13,0xbf1dbf51,0x3f423f6a,0xbf27becf,0xbf7fbf6f,0xbd97beb8,
0x3f463f75,0xbf22be95,0xbf46bf75,0x3f223e95,0x3dc93ef1,0xbf7fbf62,0xbdc9bef1,0x3f7f3f62,0xbf22be95,0xbf46bf75,0x3f223e95,0x3f463f75,
0xbf7fbf62,0xbdc9bef1,0x3f7f3f62,0x3dc93ef1,0xbf42beb8,0xbf27bf6f,0x3f7f3f6a,0xbd973ecf,0xbf77bf7a,0x3e89be60,0x3efc3f58,0xbf5fbf09,
0xbea1bf39,0x3f733f31,0xbee63cc9,0xbf65bf80,0x3f1d3e2f,0x3f4a3f7c,0xbf7ebf51,0xbdfbbf13,0xbf04bf67,0x3f5c3edb,0xbf5cbedb,0xbf04bf67,
0x3f183d49,0x3f4e3f80,0xbf4ebf80,0x3f183d49,0x3f783f71,0xbe793eac,0x3e79beac,0x3f783f71,0x3e163f2c,0xbf7dbf3e,0x3f7d3f3e,0x3e163f2c,
0x3f6f3efc,0x3eb83f5f,0x3ecfbe89,0x3f6a3f77,0x3f093f73,0xbf58bea1,0x3f7a3f65,0xbe603ee6,0xbf39bdfb,0xbf31bf7e,0xbcc93f1d,0xbf80bf4a,
0xbf51bf7f,0x3f13bd97,0xbf7cbf27,0xbe2fbf42,0x3e483f55,0xbf7bbf0e,0x3e483f55,0xbf7bbf0e,0xbf7bbf0e,0xbe48bf55,0xbf7bbf0e,0xbe48bf55,
0xbe48bf55,0x3f7b3f0e,0xbe48bf55,0x3f7b3f0e,0x3f7b3f0e,0x3e483f55,0x3f7b3f0e,0x3e483f55,0xbf80bf1d,0xbcc9bf4a,0xbf39bf7e,0x3f31bdfb,
0x3e2fbf27,0x3f7c3f42,0x3f513d97,0x3f133f7f,0x3f6f3f5f,0xbeb83efc,0x3ecf3f77,0xbf6abe89,0xbf093ea1,0xbf58bf73,0xbf7abee6,0xbe60bf65,
0x3e16bf3e,0x3f7d3f2c,0x3f7d3f2c,0xbe163f3e,0x3f5c3f67,0xbf043edb,0xbf043edb,0xbf5cbf67,0xbf4e3d49,0xbf18bf80,0xbf18bf80,0x3f4ebd49,
0xbe79bf71,0x3f783eac,0x3f783eac,0x3e793f71,0x3f733f39,0xbea13f31,0xbf65bcc9,0xbee6bf80,0xbf4a3e2f,0xbf1dbf7c,0x3dfbbf51,0x3f7e3f13,
0xbd97bf6a,0x3f7f3ecf,0x3f423f6f,0xbf273eb8,0x3f5f3f58,0xbefc3f09,0xbf77be60,0xbe89bf7a,0xbef13f22,0xbf62bf46,0x3ef1bf22,0x3f623f46,
0xbe95bf7f,0x3f753dc9,0x3e953f7f,0xbf75bdc9,0x3f623f46,0xbef13f22,0xbf62bf46,0x3ef1bf22,0xbf75bdc9,0xbe95bf7f,0x3f753dc9,0x3e953f7f,
0xbf4abf51,0x3f1dbf13,0x3dfb3f7c,0xbf7ebe2f,0x3f7f3eb8,0xbd973f6f,0xbf27bf6a,0x3f42becf,0xbf5f3e60,0xbefcbf7a,0x3f773f09,0xbe893f58,
0x3ee6bf39,0x3f653f31,0xbf733cc9,0xbea1bf80,0x3f3ebf04,0x3f2c3f5c,0xbf2cbf5c,0x3f3ebf04,0xbedb3f4e,0xbf67bf18,0x3f673f18,0xbedb3f4e,
0x3d49bf78,0x3f803e79,0xbf80be79,0x3d49bf78,0x3eac3f7d,0xbf713e16,0x3f71be16,0x3eac3f7d,0x3f093f65,0xbf583ee6,0x3f7a3ea1,0xbe603f73,
0xbf31bf4a,0x3f39bf1d,0xbf80bdfb,0x3cc9bf7e,0x3f513f27,0xbf133f42,0x3f7cbd97,0x3e2f3f7f,0xbf6abefc,0x3ecfbf5f,0xbf6f3e89,0xbeb8bf77,
0xbf6d3ec4,0xbec4bf6d,0xbf6d3ec4,0xbec4bf6d,0x3f6dbec4,0x3ec43f6d,0x3f6dbec4,0x3ec43f6d,0xbf6d3ec4,0xbec4bf6d,0xbf6d3ec4,0xbec4bf6d,
0x3f6dbec4,0x3ec43f6d,0x3f6dbec4,0x3ec43f6d,0xbe60bf73,0x3f7abea1,0x3f09bf65,0x3f583ee6,0x3cc93f7e,0xbf803dfb,0xbf313f4a,0xbf39bf1d,
0x3e2fbf7f,0x3f7c3d97,0x3f51bf27,0x3f133f42,0xbeb83f77,0xbf6fbe89,0xbf6a3efc,0xbecfbf5f,0x3f80be79,0x3d493f78,0x3d493f78,0xbf803e79,
0xbf71be16,0x3eacbf7d,0x3eacbf7d,0x3f713e16,0x3f3e3f04,0xbf2c3f5c,0xbf2c3f5c,0xbf3ebf04,0xbedbbf4e,0x3f67bf18,0x3f67bf18,0x3edb3f4e,
0xbdfb3f7c,0xbf7e3e2f,0xbf1dbf13,0x3f4abf51,0x3f27bf6a,0x3f423ecf,0x3d973f6f,0xbf7f3eb8,0xbf773f09,0xbe89bf58,0x3efcbf7a,0x3f5f3e60,
0x3f733cc9,0xbea13f80,0xbf653f31,0xbee6bf39,0xbf753dc9,0x3e95bf7f,0x3f75bdc9,0xbe953f7f,0x3ef13f22,0xbf623f46,0xbef1bf22,0x3f62bf46,
0x3e95bf7f,0x3f75bdc9,0xbe953f7f,0xbf753dc9,0xbf623f46,0xbef1bf22,0x3f62bf46,0x3ef13f22,0x3ee6bf80,0x3f65bcc9,0xbf733f39,0xbea1bf31,
0xbf7e3f13,0xbdfbbf51,0x3f4a3e2f,0xbf1d3f7c,0x3f273eb8,0xbf423f6f,0x3d97bf6a,0x3f7fbecf,0x3e89bf7a,0x3f77be60,0xbf5f3f58,0xbefcbf09,
0x3f4e3d49,0xbf183f80,0x3f18bf80,0x3f4e3d49,0x3e79bf71,0x3f78beac,0xbf783eac,0x3e79bf71,0xbf7d3f2c,0xbe16bf3e,0x3e163f3e,0xbf7d3f2c,
0x3f043edb,0xbf5c3f67,0x3f5cbf67,0x3f043edb,0xbf393f7e,0xbf31bdfb,0xbcc93f4a,0xbf803f1d,0x3f51bd97,0xbf133f7f,0x3f7cbf42,0x3e2f3f27,
0x3ecfbf77,0x3f6abe89,0xbeb8befc,0x3f6fbf5f,0xbf7a3ee6,0x3e60bf65,0xbf583f73,0xbf09bea1,0xbf0ebe48,0x3f55bf7b,0xbf0ebe48,0x3f55bf7b,
0xbf553f7b,0xbf0ebe48,0xbf553f7b,0xbf0ebe48,0x3f0e3e48,0xbf553f7b,0x3f0e3e48,0xbf553f7b,0x3f55bf7b,0x3f0e3e48,0x3f55bf7b,0x3f0e3e48,
0x3f6abf77,0x3ecf3e89,0x3f6fbefc,0xbeb83f5f,0xbe60bee6,0x3f7abf65,0x3f09bf73,0x3f58bea1,0xbf803f4a,0xbcc9bf1d,0xbf393dfb,0x3f31bf7e,
0xbe2f3f42,0xbf7c3f27,0xbf513f7f,0xbf13bd97,0x3e793eac,0xbf783f71,0xbf783f71,0xbe79beac,0x3f7dbf3e,0xbe163f2c,0xbe163f2c,0xbf7d3f3e,
0x3f04bf67,0x3f5cbedb,0x3f5cbedb,0xbf043f67,0xbf183d49,0x3f4ebf80,0x3f4ebf80,0x3f18bd49,0xbf7f3f6a,0xbd97becf,0x3f27bf6f,0x3f42beb8,
0xbefc3f58,0xbf5f3f09,0xbe89be60,0x3f77bf7a,0x3ee63cc9,0xbf653f80,0xbf733f31,0x3ea1bf39,0x3f7ebf51,0xbdfb3f13,0xbf4a3f7c,0xbf1d3e2f,
0x3dc9bef1,0x3f7fbf62,0xbdc93ef1,0xbf7f3f62,0xbf223e95,0x3f46bf75,0x3f22be95,0xbf463f75,0xbf7f3f62,0x3dc9bef1,0x3f7fbf62,0xbdc93ef1,
0xbf463f75,0xbf223e95,0x3f46bf75,0x3f22be95,0x3f77bf58,0xbe893f09,0xbefc3e60,0x3f5fbf7a,0x3f73bf80,0x3ea1bcc9,0xbf653f39,0x3ee6bf31,
0x3f1dbf51,0x3f4abf13,0xbf7e3f7c,0xbdfbbe2f,0x3d97beb8,0x3f7fbf6f,0xbf423f6a,0xbf273ecf,0xbedb3f18,0xbf673f4e,0x3f67bf4e,0xbedb3f18,
0xbd493e79,0xbf803f78,0x3f80bf78,0xbd493e79,0x3eacbe16,0xbf713f7d,0x3f71bf7d,0x3eacbe16,0x3f2cbf04,0xbf3e3f5c,0x3f3ebf5c,0x3f2cbf04,
0xbf513f42,0x3f13bf27,0xbf7c3f7f,0xbe2f3d97,0xbf6a3f5f,0x3ecfbefc,0xbf6f3f77,0xbeb83e89,0xbf7a3f73,0x3e60bea1,0xbf583f65,0xbf093ee6,
0xbf803f7e,0x3cc9bdfb,0xbf393f4a,0xbf313f1d,0x3f803f80,0xbf353f35,0x3f803f80,0xbf353f35,0x3f803f80,0xbf353f35,0x3f803f80,0xbf353f35,
0x3f803f80,0xbf353f35,0x3f803f80,0xbf353f35,0x3f803f80,0xbf353f35,0x3f803f80,0xbf353f35,0xbf7cbf7f,0x3e2f3d97,0xbf13bf27,0x3f513f42,
0xbf6fbf77,0x3eb83e89,0xbecfbefc,0x3f6a3f5f,0xbf58bf65,0x3f093ee6,0xbe60bea1,0x3f7a3f73,0xbf39bf4a,0x3f313f1d,0xbcc9bdfb,0x3f803f7e,
0x3f713f7d,0xbeacbe16,0xbeacbe16,0xbf71bf7d,0x3f3e3f5c,0xbf2cbf04,0xbf2cbf04,0xbf3ebf5c,0x3edb3f18,0xbf67bf4e,0xbf67bf4e,0xbedbbf18,
0x3d493e79,0xbf80bf78,0xbf80bf78,0xbd49be79,0xbf5fbf7a,0x3efc3e60,0x3f773f58,0x3e893f09,0xbee6bf31,0x3f653f39,0x3f733f80,0xbea1bcc9,
0x3dfbbe2f,0x3f7e3f7c,0x3f1d3f51,0xbf4abf13,0x3f273ecf,0x3f423f6a,0x3d973eb8,0xbf7fbf6f,0x3f463f75,0xbf22be95,0xbf46bf75,0x3f223e95,
0x3dc93ef1,0xbf7fbf62,0xbdc9bef1,0x3f7f3f62,0xbf22be95,0xbf46bf75,0x3f223e95,0x3f463f75,0xbf7fbf62,0xbdc9bef1,0x3f7f3f62,0x3dc93ef1,
0xbf27bf6f,0x3f423eb8,0xbd973ecf,0xbf7fbf6a,0x3e89be60,0x3f773f7a,0xbf5fbf09,0xbefcbf58,0x3f733f31,0x3ea13f39,0xbf65bf80,0x3ee6bcc9,
0x3f4a3f7c,0xbf1dbe2f,0xbdfbbf13,0x3f7e3f51,0x3f043f67,0xbf5cbedb,0x3f5c3edb,0x3f043f67,0xbf18bd49,0xbf4ebf80,0x3f4e3f80,0xbf18bd49,
0xbf78bf71,0x3e79beac,0xbe793eac,0xbf78bf71,0xbe16bf2c,0x3f7d3f3e,0xbf7dbf3e,0xbe16bf2c,0xbeb8bf5f,0x3f6f3efc,0xbf6abf77,0x3ecfbe89,
0x3f583ea1,0x3f093f73,0x3e60bee6,0x3f7a3f65,0x3f313f7e,0xbf39bdfb,0x3f803f4a,0xbcc93f1d,0xbf133d97,0xbf51bf7f,0x3e2f3f42,0xbf7cbf27,
0x3e483f55,0xbf7bbf0e,0x3e483f55,0xbf7bbf0e,0xbf7bbf0e,0xbe48bf55,0xbf7bbf0e,0xbe48bf55,0xbe48bf55,0x3f7b3f0e,0xbe48bf55,0x3f7b3f0e,
0x3f7b3f0e,0x3e483f55,0x3f7b3f0e,0x3e483f55,0xbcc9bf4a,0x3f803f1d,0x3f31bdfb,0x3f393f7e,0x3f7c3f42,0xbe2f3f27,0x3f133f7f,0xbf51bd97,
0xbeb83efc,0xbf6fbf5f,0xbf6abe89,0xbecfbf77,0xbf58bf73,0x3f09bea1,0xbe60bf65,0x3f7a3ee6,0xbe163f3e,0xbf7dbf2c,0xbf7dbf2c,0x3e16bf3e,
0xbf5cbf67,0x3f04bedb,0x3f04bedb,0x3f5c3f67,0x3f4ebd49,0x3f183f80,0x3f183f80,0xbf4e3d49,0x3e793f71,0xbf78beac,0xbf78beac,0xbe79bf71,
0x3ea1bf31,0x3f733f39,0x3ee63f80,0xbf65bcc9,0x3f1d3f7c,0xbf4a3e2f,0xbf7ebf13,0x3dfbbf51,0xbf7fbecf,0xbd97bf6a,0x3f27beb8,0x3f423f6f,
0x3efcbf09,0x3f5f3f58,0x3e893f7a,0xbf77be60,0xbef13f22,0xbf62bf46,0x3ef1bf22,0x3f623f46,0xbe95bf7f,0x3f753dc9,0x3e953f7f,0xbf75bdc9,
0x3f623f46,0xbef13f22,0xbf62bf46,0x3ef1bf22,0xbf75bdc9,0xbe95bf7f,0x3f753dc9,0x3e953f7f,0x3f1dbf13,0x3f4a3f51,0xbf7ebe2f,0xbdfbbf7c,
0xbd973f6f,0xbf7fbeb8,0x3f42becf,0x3f273f6a,0xbefcbf7a,0x3f5fbe60,0xbe893f58,0xbf77bf09,0x3f653f31,0xbee63f39,0xbea1bf80,0x3f73bcc9,
0xbf3e3f04,0xbf2cbf5c,0x3f2c3f5c,0xbf3e3f04,0x3edbbf4e,0x3f673f18,0xbf67bf18,0x3edbbf4e,0xbd493f78,0xbf80be79,0x3f803e79,0xbd493f78,
0xbeacbf7d,0x3f71be16,0xbf713e16,0xbeacbf7d,0x3f58bee6,0x3f093f65,0x3e60bf73,0x3f7a3ea1,0xbf393f1d,0xbf31bf4a,0xbcc93f7e,0xbf80bdfb,
0x3f13bf42,0x3f513f27,0xbe2fbf7f,0x3f7cbd97,0xbecf3f5f,0xbf6abefc,0x3eb83f77,0xbf6f3e89,0xbf6d3ec4,0xbec4bf6d,0xbf6d3ec4,0xbec4bf6d,
0x3f6dbec4,0x3ec43f6d,0x3f6dbec4,0x3ec43f6d,0xbf6d3ec4,0xbec4bf6d,0xbf6d3ec4,0xbec4bf6d,0x3f6dbec4,0x3ec43f6d,0x3f6dbec4,0x3ec43f6d,
0x3f7abea1,0x3e603f73,0x3f583ee6,0xbf093f65,0xbf803dfb,0xbcc9bf7e,0xbf39bf1d,0x3f31bf4a,0x3f7c3d97,0xbe2f3f7f,0x3f133f42,0xbf513f27,
0xbf6fbe89,0x3eb8bf77,0xbecfbf5f,0x3f6abefc,0xbf803e79,0xbd49bf78,0xbd49bf78,0x3f80be79,0x3f713e16,0xbeac3f7d,0xbeac3f7d,0xbf71be16,
0xbf3ebf04,0x3f2cbf5c,0x3f2cbf5c,0x3f3e3f04,0x3edb3f4e,0xbf673f18,0xbf673f18,0xbedbbf4e,0x3f7ebe2f,0xbdfb3f7c,0xbf4a3f51,0xbf1dbf13,
0xbf42becf,0x3f27bf6a,0x3f7fbeb8,0x3d973f6f,0x3e893f58,0xbf773f09,0xbf5fbe60,0x3efcbf7a,0x3ea1bf80,0x3f733cc9,0x3ee63f39,0xbf653f31,
0xbf753dc9,0x3e95bf7f,0x3f75bdc9,0xbe953f7f,0x3ef13f22,0xbf623f46,0xbef1bf22,0x3f62bf46,0x3e95bf7f,0x3f75bdc9,0xbe953f7f,0xbf753dc9,
0xbf623f46,0xbef1bf22,0x3f62bf46,0x3ef13f22,0x3f65bcc9,0xbee63f80,0xbea1bf31,0x3f73bf39,0xbdfbbf51,0x3f7ebf13,0xbf1d3f7c,0xbf4abe2f,
0xbf423f6f,0xbf27beb8,0x3f7fbecf,0xbd973f6a,0x3f77be60,0xbe893f7a,0xbefcbf09,0x3f5fbf58,0xbf4ebd49,0x3f18bf80,0xbf183f80,0xbf4ebd49,
0xbe793f71,0xbf783eac,0x3f78beac,0xbe793f71,0x3f7dbf2c,0x3e163f3e,0xbe16bf3e,0x3f7dbf2c,0xbf04bedb,0x3f5cbf67,0xbf5c3f67,0xbf04bedb,
0x3f313dfb,0xbf393f7e,0x3f80bf1d,0xbcc93f4a,0x3f13bf7f,0x3f51bd97,0xbe2fbf27,0x3f7cbf42,0xbf6a3e89,0x3ecfbf77,0xbf6f3f5f,0xbeb8befc,
0xbe603f65,0xbf7a3ee6,0x3f093ea1,0xbf583f73,0xbf0ebe48,0x3f55bf7b,0xbf0ebe48,0x3f55bf7b,0xbf553f7b,0xbf0ebe48,0xbf553f7b,0xbf0ebe48,
0x3f0e3e48,0xbf553f7b,0x3f0e3e48,0xbf553f7b,0x3f55bf7b,0x3f0e3e48,0x3f55bf7b,0x3f0e3e48,0x3ecf3e89,0xbf6a3f77,0xbeb83f5f,0xbf6f3efc,
0x3f7abf65,0x3e603ee6,0x3f58bea1,0xbf093f73,0xbcc9bf1d,0x3f80bf4a,0x3f31bf7e,0x3f39bdfb,0xbf7c3f27,0x3e2fbf42,0xbf13bd97,0x3f51bf7f,
0xbe79beac,0x3f78bf71,0x3f78bf71,0x3e793eac,0xbf7d3f3e,0x3e16bf2c,0x3e16bf2c,0x3f7dbf3e,0xbf043f67,0xbf5c3edb,0xbf5c3edb,0x3f04bf67,
0x3f18bd49,0xbf4e3f80,0xbf4e3f80,0xbf183d49,0x3d973ecf,0xbf7f3f6a,0xbf423eb8,0x3f27bf6f,0x3f5fbf09,0xbefc3f58,0xbf773f7a,0xbe89be60,
0x3f65bf80,0x3ee63cc9,0xbea13f39,0xbf733f31,0x3dfbbf13,0x3f7ebf51,0x3f1dbe2f,0xbf4a3f7c,0x3dc9bef1,0x3f7fbf62,0xbdc93ef1,0xbf7f3f62,
0xbf223e95,0x3f46bf75,0x3f22be95,0xbf463f75,0xbf7f3f62,0x3dc9bef1,0x3f7fbf62,0xbdc93ef1,0xbf463f75,0xbf223e95,0x3f46bf75,0x3f22be95,
0xbe893f09,0xbf773f58,0x3f5fbf7a,0x3efcbe60,0x3ea1bcc9,0xbf733f80,0x3ee6bf31,0x3f65bf39,0x3f4abf13,0xbf1d3f51,0xbdfbbe2f,0x3f7ebf7c,
0x3f7fbf6f,0xbd973eb8,0xbf273ecf,0x3f42bf6a,0x3edbbf18,0x3f67bf4e,0xbf673f4e,0x3edbbf18,0x3d49be79,0x3f80bf78,0xbf803f78,0x3d49be79,
0xbeac3e16,0x3f71bf7d,0xbf713f7d,0xbeac3e16,0xbf2c3f04,0x3f3ebf5c,0xbf3e3f5c,0xbf2c3f04,0xbf133f27,0xbf513f42,0x3e2fbd97,0xbf7c3f7f,
0xbecf3efc,0xbf6a3f5f,0x3eb8be89,0xbf6f3f77,0xbe603ea1,0xbf7a3f73,0x3f09bee6,0xbf583f65,0xbcc93dfb,0xbf803f7e,0x3f31bf1d,0xbf393f4a,
0x3f803f80,0xbf353f35,0x3f803f80,0xbf353f35,0x3f803f80,0xbf353f35,0x3f803f80,0xbf353f35,0x3f803f80,0xbf353f35,0x3f803f80,0xbf353f35,
0x3f803f80,0xbf353f35,0x3f803f80,0xbf353f35,0x3e2f3d97,0x3f7c3f7f,0x3f513f42,0x3f133f27,0x3eb83e89,0x3f6f3f77,0x3f6a3f5f,0x3ecf3efc,
0x3f093ee6,0x3f583f65,0x3f7a3f73,0x3e603ea1,0x3f313f1d,0x3f393f4a,0x3f803f7e,0x3cc93dfb,0xbf71bf7d,0x3eac3e16,0x3eac3e16,0x3f713f7d,
0xbf3ebf5c,0x3f2c3f04,0x3f2c3f04,0x3f3e3f5c,0xbedbbf18,0x3f673f4e,0x3f673f4e,0x3edb3f18,0xbd49be79,0x3f803f78,0x3f803f78,0x3d493e79,
0xbefcbe60,0xbf5fbf7a,0xbe89bf09,0x3f773f58,0xbf65bf39,0xbee6bf31,0x3ea13cc9,0x3f733f80,0xbf7ebf7c,0x3dfbbe2f,0x3f4a3f13,0x3f1d3f51,
0xbf42bf6a,0x3f273ecf,0x3f7f3f6f,0x3d973eb8,0x3f463f75,0xbf22be95,0xbf46bf75,0x3f223e95,0x3dc93ef1,0xbf7fbf62,0xbdc9bef1,0x3f7f3f62,
0xbf22be95,0xbf46bf75,0x3f223e95,0x3f463f75,0xbf7fbf62,0xbdc9bef1,0x3f7f3f62,0x3dc93ef1,0x3f423eb8,0x3f273f6f,0xbf7fbf6a,0x3d97becf,
0x3f773f7a,0xbe893e60,0xbefcbf58,0x3f5f3f09,0x3ea13f39,0xbf73bf31,0x3ee6bcc9,0x3f653f80,0xbf1dbe2f,0xbf4abf7c,0x3f7e3f51,0x3dfb3f13,
0xbf04bf67,0x3f5c3edb,0xbf5cbedb,0xbf04bf67,0x3f183d49,0x3f4e3f80,0xbf4ebf80,0x3f183d49,0x3f783f71,0xbe793eac,0x3e79beac,0x3f783f71,
0x3e163f2c,0xbf7dbf3e,0x3f7d3f3e,0x3e163f2c,0xbf6fbefc,0xbeb8bf5f,0xbecf3e89,0xbf6abf77,0xbf09bf73,0x3f583ea1,0xbf7abf65,0x3e60bee6,
0x3f393dfb,0x3f313f7e,0x3cc9bf1d,0x3f803f4a,0x3f513f7f,0xbf133d97,0x3f7c3f27,0x3e2f3f42,0x3e483f55,0xbf7bbf0e,0x3e483f55,0xbf7bbf0e,
0xbf7bbf0e,0xbe48bf55,0xbf7bbf0e,0xbe48bf55,0xbe48bf55,0x3f7b3f0e,0xbe48bf55,0x3f7b3f0e,0x3f7b3f0e,0x3e483f55,0x3f7b3f0e,0x3e483f55,
0x3f803f1d,0x3cc93f4a,0x3f393f7e,0xbf313dfb,0xbe2f3f27,0xbf7cbf42,0xbf51bd97,0xbf13bf7f,0xbf6fbf5f,0x3eb8befc,0xbecfbf77,0x3f6a3e89,
0x3f09bea1,0x3f583f73,0x3f7a3ee6,0x3e603f65,0x3e16bf3e,0x3f7d3f2c,0x3f7d3f2c,0xbe163f3e,0x3f5c3f67,0xbf043edb,0xbf043edb,0xbf5cbf67,
0xbf4e3d49,0xbf18bf80,0xbf18bf80,0x3f4ebd49,0xbe79bf71,0x3f783eac,0x3f783eac,0x3e793f71,0xbf73bf39,0x3ea1bf31,0x3f653cc9,0x3ee63f80,
0x3f4abe2f,0x3f1d3f7c,0xbdfb3f51,0xbf7ebf13,0x3d973f6a,0xbf7fbecf,0xbf42bf6f,0x3f27beb8,0xbf5fbf58,0x3efcbf09,0x3f773e60,0x3e893f7a,
0xbef13f22,0xbf62bf46,0x3ef1bf22,0x3f623f46,0xbe95bf7f,0x3f753dc9,0x3e953f7f,0xbf75bdc9,0x3f623f46,0xbef13f22,0xbf62bf46,0x3ef1bf22,
0xbf75bdc9,0xbe95bf7f,0x3f753dc9,0x3e953f7f,0x3f4a3f51,0xbf1d3f13,0xbdfbbf7c,0x3f7e3e2f,0xbf7fbeb8,0x3d97bf6f,0x3f273f6a,0xbf423ecf,
0x3f5fbe60,0x3efc3f7a,0xbf77bf09,0x3e89bf58,0xbee63f39,0xbf65bf31,0x3f73bcc9,0x3ea13f80,0x3f3ebf04,0x3f2c3f5c,0xbf2cbf5c,0x3f3ebf04,
0xbedb3f4e,0xbf67bf18,0x3f673f18,0xbedb3f4e,0x3d49bf78,0x3f803e79,0xbf80be79,0x3d49bf78,0x3eac3f7d,0xbf713e16,0x3f71be16,0x3eac3f7d,
0xbf09bf65,0x3f58bee6,0xbf7abea1,0x3e60bf73,0x3f313f4a,0xbf393f1d,0x3f803dfb,0xbcc93f7e,0xbf51bf27,0x3f13bf42,0xbf7c3d97,0xbe2fbf7f,
0x3f6a3efc,0xbecf3f5f,0x3f6fbe89,0x3eb83f77,0xbf6d3ec4,0xbec4bf6d,0xbf6d3ec4,0xbec4bf6d,0x3f6dbec4,0x3ec43f6d,0x3f6dbec4,0x3ec43f6d,
0xbf6d3ec4,0xbec4bf6d,0xbf6d3ec4,0xbec4bf6d,0x3f6dbec4,0x3ec43f6d,0x3f6dbec4,0x3ec43f6d,0x3e603f73,0xbf7a3ea1,0xbf093f65,0xbf58bee6,
0xbcc9bf7e,0x3f80bdfb,0x3f31bf4a,0x3f393f1d,0xbe2f3f7f,0xbf7cbd97,0xbf513f27,0xbf13bf42,0x3eb8bf77,0x3f6f3e89,0x3f6abefc,0x3ecf3f5f,
0x3f80be79,0x3d493f78,0x3d493f78,0xbf803e79,0xbf71be16,0x3eacbf7d,0x3eacbf7d,0x3f713e16,0x3f3e3f04,0xbf2c3f5c,0xbf2c3f5c,0xbf3ebf04,
0xbedbbf4e,0x3f67bf18,0x3f67bf18,0x3edb3f4e,0x3dfbbf7c,0x3f7ebe2f,0x3f1d3f13,0xbf4a3f51,0xbf273f6a,0xbf42becf,0xbd97bf6f,0x3f7fbeb8,
0x3f77bf09,0x3e893f58,0xbefc3f7a,0xbf5fbe60,0xbf73bcc9,0x3ea1bf80,0x3f65bf31,0x3ee63f39,0xbf753dc9,0x3e95bf7f,0x3f75bdc9,0xbe953f7f,
0x3ef13f22,0xbf623f46,0xbef1bf22,0x3f62bf46,0x3e95bf7f,0x3f75bdc9,0xbe953f7f,0xbf753dc9,0xbf623f46,0xbef1bf22,0x3f62bf46,0x3ef13f22,
0xbee63f80,0xbf653cc9,0x3f73bf39,0x3ea13f31,0x3f7ebf13,0x3dfb3f51,0xbf4abe2f,0x3f1dbf7c,0xbf27beb8,0x3f42bf6f,0xbd973f6a,0xbf7f3ecf,
0xbe893f7a,0xbf773e60,0x3f5fbf58,0x3efc3f09,0x3f4e3d49,0xbf183f80,0x3f18bf80,0x3f4e3d49,0x3e79bf71,0x3f78beac,0xbf783eac,0x3e79bf71,
0xbf7d3f2c,0xbe16bf3e,0x3e163f3e,0xbf7d3f2c,0x3f043edb,0xbf5c3f67,0x3f5cbf67,0x3f043edb,0x3f39bf7e,0x3f313dfb,0x3cc9bf4a,0x3f80bf1d,
0xbf513d97,0x3f13bf7f,0xbf7c3f42,0xbe2fbf27,0xbecf3f77,0xbf6a3e89,0x3eb83efc,0xbf6f3f5f,0x3f7abee6,0xbe603f65,0x3f58bf73,0x3f093ea1,
0xbf0ebe48,0x3f55bf7b,0xbf0ebe48,0x3f55bf7b,0xbf553f7b,0xbf0ebe48,0xbf553f7b,0xbf0ebe48,0x3f0e3e48,0xbf553f7b,0x3f0e3e48,0xbf553f7b,
0x3f55bf7b,0x3f0e3e48,0x3f55bf7b,0x3f0e3e48,0xbf6a3f77,0xbecfbe89,0xbf6f3efc,0x3eb8bf5f,0x3e603ee6,0xbf7a3f65,0xbf093f73,0xbf583ea1,
0x3f80bf4a,0x3cc93f1d,0x3f39bdfb,0xbf313f7e,0x3e2fbf42,0x3f7cbf27,0x3f51bf7f,0x3f133d97,0x3e793eac,0xbf783f71,0xbf783f71,0xbe79beac,
0x3f7dbf3e,0xbe163f2c,0xbe163f2c,0xbf7d3f3e,0x3f04bf67,0x3f5cbedb,0x3f5cbedb,0xbf043f67,0xbf183d49,0x3f4ebf80,0x3f4ebf80,0x3f18bd49,
0x3f7fbf6a,0x3d973ecf,0xbf273f6f,0xbf423eb8,0x3efcbf58,0x3f5fbf09,0x3e893e60,0xbf773f7a,0xbee6bcc9,0x3f65bf80,0x3f73bf31,0xbea13f39,
0xbf7e3f51,0x3dfbbf13,0x3f4abf7c,0x3f1dbe2f,0x3dc9bef1,0x3f7fbf62,0xbdc93ef1,0xbf7f3f62,0xbf223e95,0x3f46bf75,0x3f22be95,0xbf463f75,
0xbf7f3f62,0x3dc9bef1,0x3f7fbf62,0xbdc93ef1,0xbf463f75,0xbf223e95,0x3f46bf75,0x3f22be95,0xbf773f58,0x3e89bf09,0x3efcbe60,0xbf5f3f7a,
0xbf733f80,0xbea13cc9,0x3f65bf39,0xbee63f31,0xbf1d3f51,0xbf4a3f13,0x3f7ebf7c,0x3dfb3e2f,0xbd973eb8,0xbf7f3f6f,0x3f42bf6a,0x3f27becf,
0xbedb3f18,0xbf673f4e,0x3f67bf4e,0xbedb3f18,0xbd493e79,0xbf803f78,0x3f80bf78,0xbd493e79,0x3eacbe16,0xbf713f7d,0x3f71bf7d,0x3eacbe16,
0x3f2cbf04,0xbf3e3f5c,0x3f3ebf5c,0x3f2cbf04,0x3f51bf42,0xbf133f27,0x3f7cbf7f,0x3e2fbd97,0x3f6abf5f,0xbecf3efc,0x3f6fbf77,0x3eb8be89,
0x3f7abf73,0xbe603ea1,0x3f58bf65,0x3f09bee6,0x3f80bf7e,0xbcc93dfb,0x3f39bf4a,0x3f31bf1d,0x3f803f80,0x3f803f80,0x3f803f80,0x3f803f80,
0x0,0x0,0x0,0x0,0x3f803f80,0x3f803f80,0x3f803f80,0x3f803f80,0x0,0x0,0x0,0x0,
0x3f803f80,0x3f803f80,0x3f803f80,0x3f803f80,0x0,0x0,0x0,0x0,0x3f803f80,0x3f803f80,0x3f803f80,0x3f803f80,
0x0,0x0,0x0,0x0,0x3e480000,0x3f0e3ec4,0x3f553f35,0x3f7b3f6d,0x3f7b3f80,0x3f553f6d,0x3f0e3f35,0x3e483ec4,
0x3f7b3f80,0x3f553f6d,0x3f0e3f35,0x3e483ec4,0xbe480000,0xbf0ebec4,0xbf55bf35,0xbf7bbf6d,0xbe480000,0xbf0ebec4,0xbf55bf35,0xbf7bbf6d,
0xbf7bbf80,0xbf55bf6d,0xbf0ebf35,0xbe48bec4,0xbf7bbf80,0xbf55bf6d,0xbf0ebf35,0xbe48bec4,0x3e480000,0x3f0e3ec4,0x3f553f35,0x3f7b3f6d,
0xbf6dbf80,0xbec4bf35,0x3ec40000,0x3f6d3f35,0xbec40000,0xbf6dbf35,0xbf6dbf80,0xbec4bf35,0x3f6d3f80,0x3ec43f35,0xbec40000,0xbf6dbf35,
0x3ec40000,0x3f6d3f35,0x3f6d3f80,0x3ec43f35,0xbf6dbf80,0xbec4bf35,0x3ec40000,0x3f6d3f35,0xbec40000,0xbf6dbf35,0xbf6dbf80,0xbec4bf35,
0x3f6d3f80,0x3ec43f35,0xbec40000,0xbf6dbf35,0x3ec40000,0x3f6d3f35,0x3f6d3f80,0x3ec43f35,0xbf55bf80,0x3e48bec4,0x3f7b3f35,0x3f0e3f6d,
0x3f0e0000,0x3f7b3f6d,0x3e483f35,0xbf55bec4,0x3f0e0000,0x3f7b3f6d,0x3e483f35,0xbf55bec4,0x3f553f80,0xbe483ec4,0xbf7bbf35,0xbf0ebf6d,
0x3f553f80,0xbe483ec4,0xbf7bbf35,0xbf0ebf6d,0xbf0e0000,0xbf7bbf6d,0xbe48bf35,0x3f553ec4,0xbf0e0000,0xbf7bbf6d,0xbe48bf35,0x3f553ec4,
0xbf55bf80,0x3e48bec4,0x3f7b3f35,0x3f0e3f6d,0x3f353f80,0xbf350000,0xbf35bf80,0x3f350000,0x3f350000,0x3f353f80,0xbf350000,0xbf35bf80,
0x3f353f80,0xbf350000,0xbf35bf80,0x3f350000,0x3f350000,0x3f353f80,0xbf350000,0xbf35bf80,0x3f353f80,0xbf350000,0xbf35bf80,0x3f350000,
0x3f350000,0x3f353f80,0xbf350000,0xbf35bf80,0x3f353f80,0xbf350000,0xbf35bf80,0x3f350000,0x3f350000,0x3f353f80,0xbf350000,0xbf35bf80,
0xbf550000,0xbe48bf6d,0x3f7b3f35,0xbf0e3ec4,0xbf0ebf80,0x3f7b3ec4,0xbe483f35,0xbf55bf6d,0xbf0ebf80,0x3f7b3ec4,0xbe483f35,0xbf55bf6d,
0x3f550000,0x3e483f6d,0xbf7bbf35,0x3f0ebec4,0x3f550000,0x3e483f6d,0xbf7bbf35,0x3f0ebec4,0x3f0e3f80,0xbf7bbec4,0x3e48bf35,0x3f553f6d,
0x3f0e3f80,0xbf7bbec4,0x3e48bf35,0x3f553f6d,0xbf550000,0xbe48bf6d,0x3f7b3f35,0xbf0e3ec4,0xbec4bf80,0x3f6d3f35,0xbf6d0000,0x3ec4bf35,
0xbf6d0000,0x3ec4bf35,0x3ec43f80,0xbf6dbf35,0x3ec43f80,0xbf6dbf35,0x3f6d0000,0xbec43f35,0x3f6d0000,0xbec43f35,0xbec4bf80,0x3f6d3f35,
0xbec4bf80,0x3f6d3f35,0xbf6d0000,0x3ec4bf35,0xbf6d0000,0x3ec4bf35,0x3ec43f80,0xbf6dbf35,0x3ec43f80,0xbf6dbf35,0x3f6d0000,0xbec43f35,
0x3f6d0000,0xbec43f35,0xbec4bf80,0x3f6d3f35,0x3e483f80,0xbf0ebf6d,0x3f553f35,0xbf7bbec4,0xbf7b0000,0x3f55bec4,0xbf0e3f35,0x3e48bf6d,
0xbf7b0000,0x3f55bec4,0xbf0e3f35,0x3e48bf6d,0xbe48bf80,0x3f0e3f6d,0xbf55bf35,0x3f7b3ec4,0xbe48bf80,0x3f0e3f6d,0xbf55bf35,0x3f7b3ec4,
0x3f7b0000,0xbf553ec4,0x3f0ebf35,0xbe483f6d,0x3f7b0000,0xbf553ec4,0x3f0ebf35,0xbe483f6d,0x3e483f80,0xbf0ebf6d,0x3f553f35,0xbf7bbec4,
0x80008000,0x80008000,0x80008000,0x80008000,0x3f803f80,0x3f803f80,0x3f803f80,0x3f803f80,0x80008000,0x80008000,0x80008000,0x80008000,
0x3f803f80,0x3f803f80,0x3f803f80,0x3f803f80,0x80008000,0x80008000,0x80008000,0x80008000,0x3f803f80,0x3f803f80,0x3f803f80,0x3f803f80,
0x80008000,0x80008000,0x80008000,0x80008000,0x3f803f80,0x3f803f80,0x3f803f80,0x3f803f80,0x3f7b3f80,0x3f553f6d,0x3f0e3f35,0x3e483ec4,
0xbe488000,0xbf0ebec4,0xbf55bf35,0xbf7bbf6d,0xbe480000,0xbf0ebec4,0xbf55bf35,0xbf7bbf6d,0xbf7bbf80,0xbf55bf6d,0xbf0ebf35,0xbe48bec4,
0xbf7bbf80,0xbf55bf6d,0xbf0ebf35,0xbe48bec4,0x3e488000,0x3f0e3ec4,0x3f553f35,0x3f7b3f6d,0x3e480000,0x3f0e3ec4,0x3f553f35,0x3f7b3f6d,
0x3f7b3f80,0x3f553f6d,0x3f0e3f35,0x3e483ec4,0x3ec48000,0x3f6d3f35,0x3f6d3f80,0x3ec43f35,0xbf6dbf80,0xbec4bf35,0x3ec40000,0x3f6d3f35,
0xbec48000,0xbf6dbf35,0xbf6dbf80,0xbec4bf35,0x3f6d3f80,0x3ec43f35,0xbec40000,0xbf6dbf35,0x3ec48000,0x3f6d3f35,0x3f6d3f80,0x3ec43f35,
0xbf6dbf80,0xbec4bf35,0x3ec40000,0x3f6d3f35,0xbec48000,0xbf6dbf35,0xbf6dbf80,0xbec4bf35,0x3f6d3f80,0x3ec43f35,0xbec40000,0xbf6dbf35,
0x3f0e0000,0x3f7b3f6d,0x3e483f35,0xbf55bec4,0x3f553f80,0xbe483ec4,0xbf7bbf35,0xbf0ebf6d,0x3f553f80,0xbe483ec4,0xbf7bbf35,0xbf0ebf6d,
0xbf0e8000,0xbf7bbf6d,0xbe48bf35,0x3f553ec4,0xbf0e0000,0xbf7bbf6d,0xbe48bf35,0x3f553ec4,0xbf55bf80,0x3e48bec4,0x3f7b3f35,0x3f0e3f6d,
0xbf55bf80,0x3e48bec4,0x3f7b3f35,0x3f0e3f6d,0x3f0e8000,0x3f7b3f6d,0x3e483f35,0xbf55bec4,0xbf358000,0xbf35bf80,0x3f358000,0x3f353f80,
0x3f353f80,0xbf350000,0xbf35bf80,0x3f350000,0xbf358000,0xbf35bf80,0x3f358000,0x3f353f80,0x3f353f80,0xbf350000,0xbf35bf80,0x3f350000,
0xbf358000,0xbf35bf80,0x3f358000,0x3f353f80,0x3f353f80,0xbf350000,0xbf35bf80,0x3f350000,0xbf358000,0xbf35bf80,0x3f358000,0x3f353f80,
0x3f353f80,0xbf350000,0xbf35bf80,0x3f350000,0xbf0ebf80,0x3f7b3ec4,0xbe483f35,0xbf55bf6d,0x3f558000,0x3e483f6d,0xbf7bbf35,0x3f0ebec4,
0x3f550000,0x3e483f6d,0xbf7bbf35,0x3f0ebec4,0x3f0e3f80,0xbf7bbec4,0x3e48bf35,0x3f553f6d,0x3f0e3f80,0xbf7bbec4,0x3e48bf35,0x3f553f6d,
0xbf558000,0xbe48bf6d,0x3f7b3f35,0xbf0e3ec4,0xbf550000,0xbe48bf6d,0x3f7b3f35,0xbf0e3ec4,0xbf0ebf80,0x3f7b3ec4,0xbe483f35,0xbf55bf6d,
0x3f6d8000,0xbec43f35,0xbec4bf80,0x3f6d3f35,0xbec4bf80,0x3f6d3f35,0xbf6d0000,0x3ec4bf35,0xbf6d8000,0x3ec4bf35,0x3ec43f80,0xbf6dbf35,
0x3ec43f80,0xbf6dbf35,0x3f6d0000,0xbec43f35,0x3f6d8000,0xbec43f35,0xbec4bf80,0x3f6d3f35,0xbec4bf80,0x3f6d3f35,0xbf6d0000,0x3ec4bf35,
0xbf6d8000,0x3ec4bf35,0x3ec43f80,0xbf6dbf35,0x3ec43f80,0xbf6dbf35,0x3f6d0000,0xbec43f35,0xbf7b0000,0x3f55bec4,0xbf0e3f35,0x3e48bf6d,
0xbe48bf80,0x3f0e3f6d,0xbf55bf35,0x3f7b3ec4,0xbe48bf80,0x3f0e3f6d,0xbf55bf35,0x3f7b3ec4,0x3f7b8000,0xbf553ec4,0x3f0ebf35,0xbe483f6d,
0x3f7b0000,0xbf553ec4,0x3f0ebf35,0xbe483f6d,0x3e483f80,0xbf0ebf6d,0x3f553f35,0xbf7bbec4,0x3e483f80,0xbf0ebf6d,0x3f553f35,0xbf7bbec4,
0xbf7b8000,0x3f55bec4,0xbf0e3f35,0x3e48bf6d,0x3f80,0xbf80,0x3f80,0xbf80,0x3f800000,0xbf800000,0x3f800000,0xbf800000,
0x3f80,0xbf80,0x3f80,0xbf80,0x3f800000,0xbf800000,0x3f800000,0xbf800000,0x3f80,0xbf80,0x3f80,0xbf80,
0x3f800000,0xbf800000,0x3f800000,0xbf800000,0x3f80,0xbf80,0x3f80,0xbf80,0x3f800000,0xbf800000,0x3f800000,0xbf800000,
0x3f7b0000,0xbf55bec4,0x3f0e3f35,0xbe48bf6d,0xbe483f80,0x3f0ebf6d,0xbf553f35,0x3f7bbec4,0xbe483f80,0x3f0ebf6d,0xbf553f35,0x3f7bbec4,
0xbf7b0000,0x3f553ec4,0xbf0ebf35,0x3e483f6d,0xbf7b0000,0x3f553ec4,0xbf0ebf35,0x3e483f6d,0x3e48bf80,0xbf0e3f6d,0x3f55bf35,0xbf7b3ec4,
0x3e48bf80,0xbf0e3f6d,0x3f55bf35,0xbf7b3ec4,0x3f7b0000,0xbf55bec4,0x3f0e3f35,0xbe48bf6d,0x3ec4bf80,0xbf6d3f35,0x3f6d0000,0xbec4bf35,
0xbf6d0000,0x3ec43f35,0x3ec4bf80,0xbf6d3f35,0xbec43f80,0x3f6dbf35,0xbf6d0000,0x3ec43f35,0x3f6d0000,0xbec4bf35,0xbec43f80,0x3f6dbf35,
0x3ec4bf80,0xbf6d3f35,0x3f6d0000,0xbec4bf35,0xbf6d0000,0x3ec43f35,0x3ec4bf80,0xbf6d3f35,0xbec43f80,0x3f6dbf35,0xbf6d0000,0x3ec43f35,
0x3f6d0000,0xbec4bf35,0xbec43f80,0x3f6dbf35,0x3f0ebf80,0xbf7b3ec4,0x3e483f35,0x3f55bf6d,0x3f550000,0x3e48bf6d,0xbf7b3f35,0x3f0e3ec4,
0x3f550000,0x3e48bf6d,0xbf7b3f35,0x3f0e3ec4,0xbf0e3f80,0x3f7bbec4,0xbe48bf35,0xbf553f6d,0xbf0e3f80,0x3f7bbec4,0xbe48bf35,0xbf553f6d,
0xbf550000,0xbe483f6d,0x3f7bbf35,0xbf0ebec4,0xbf550000,0xbe483f6d,0x3f7bbf35,0xbf0ebec4,0x3f0ebf80,0xbf7b3ec4,0x3e483f35,0x3f55bf6d,
0xbf353f80,0x3f350000,0x3f35bf80,0xbf350000,0x3f350000,0x3f35bf80,0xbf350000,0xbf353f80,0xbf353f80,0x3f350000,0x3f35bf80,0xbf350000,
0x3f350000,0x3f35bf80,0xbf350000,0xbf353f80,0xbf353f80,0x3f350000,0x3f35bf80,0xbf350000,0x3f350000,0x3f35bf80,0xbf350000,0xbf353f80,
0xbf353f80,0x3f350000,0x3f35bf80,0xbf350000,0x3f350000,0x3f35bf80,0xbf350000,0xbf353f80,0xbf0e0000,0xbf7b3f6d,0xbe483f35,0x3f55bec4,
0x3f55bf80,0xbe48bec4,0xbf7b3f35,0xbf0e3f6d,0x3f55bf80,0xbe48bec4,0xbf7b3f35,0xbf0e3f6d,0x3f0e0000,0x3f7bbf6d,0x3e48bf35,0xbf553ec4,
0x3f0e0000,0x3f7bbf6d,0x3e48bf35,0xbf553ec4,0xbf553f80,0x3e483ec4,0x3f7bbf35,0x3f0ebf6d,0xbf553f80,0x3e483ec4,0x3f7bbf35,0x3f0ebf6d,
0xbf0e0000,0xbf7b3f6d,0xbe483f35,0x3f55bec4,0x3f6dbf80,0x3ec4bf35,0xbec40000,0xbf6d3f35,0xbec40000,0xbf6d3f35,0xbf6d3f80,0xbec43f35,
0xbf6d3f80,0xbec43f35,0x3ec40000,0x3f6dbf35,0x3ec40000,0x3f6dbf35,0x3f6dbf80,0x3ec4bf35,0x3f6dbf80,0x3ec4bf35,0xbec40000,0xbf6d3f35,
0xbec40000,0xbf6d3f35,0xbf6d3f80,0xbec43f35,0xbf6d3f80,0xbec43f35,0x3ec40000,0x3f6dbf35,0x3ec40000,0x3f6dbf35,0x3f6dbf80,0x3ec4bf35,
0xbf7b3f80,0xbf553f6d,0xbf0e3f35,0xbe483ec4,0xbe480000,0xbf0e3ec4,0xbf553f35,0xbf7b3f6d,0xbe480000,0xbf0e3ec4,0xbf553f35,0xbf7b3f6d,
0x3f7bbf80,0x3f55bf6d,0x3f0ebf35,0x3e48bec4,0x3f7bbf80,0x3f55bf6d,0x3f0ebf35,0x3e48bec4,0x3e480000,0x3f0ebec4,0x3f55bf35,0x3f7bbf6d,
0x3e480000,0x3f0ebec4,0x3f55bf35,0x3f7bbf6d,0xbf7b3f80,0xbf553f6d,0xbf0e3f35,0xbe483ec4,0xbf808000,0x3f808000,0xbf808000,0x3f808000,
0x3f80,0xbf80,0x3f80,0xbf80,0xbf808000,0x3f808000,0xbf808000,0x3f808000,0x3f80,0xbf80,0x3f80,0xbf80,
0xbf808000,0x3f808000,0xbf808000,0x3f808000,0x3f80,0xbf80,0x3f80,0xbf80,0xbf808000,0x3f808000,0xbf808000,0x3f808000,
0x3f80,0xbf80,0x3f80,0xbf80,0xbe483f80,0x3f0ebf6d,0xbf553f35,0x3f7bbec4,0xbf7b8000,0x3f553ec4,0xbf0ebf35,0x3e483f6d,
0xbf7b0000,0x3f553ec4,0xbf0ebf35,0x3e483f6d,0x3e48bf80,0xbf0e3f6d,0x3f55bf35,0xbf7b3ec4,0x3e48bf80,0xbf0e3f6d,0x3f55bf35,0xbf7b3ec4,
0x3f7b8000,0xbf55bec4,0x3f0e3f35,0xbe48bf6d,0x3f7b0000,0xbf55bec4,0x3f0e3f35,0xbe48bf6d,0xbe483f80,0x3f0ebf6d,0xbf553f35,0x3f7bbec4,
0x3f6d8000,0xbec4bf35,0xbec43f80,0x3f6dbf35,0x3ec4bf80,0xbf6d3f35,0x3f6d0000,0xbec4bf35,0xbf6d8000,0x3ec43f35,0x3ec4bf80,0xbf6d3f35,
0xbec43f80,0x3f6dbf35,0xbf6d0000,0x3ec43f35,0x3f6d8000,0xbec4bf35,0xbec43f80,0x3f6dbf35,0x3ec4bf80,0xbf6d3f35,0x3f6d0000,0xbec4bf35,
0xbf6d8000,0x3ec43f35,0x3ec4bf80,0xbf6d3f35,0xbec43f80,0x3f6dbf35,0xbf6d0000,0x3ec43f35,0x3f550000,0x3e48bf6d,0xbf7b3f35,0x3f0e3ec4,
0xbf0e3f80,0x3f7bbec4,0xbe48bf35,0xbf553f6d,0xbf0e3f80,0x3f7bbec4,0xbe48bf35,0xbf553f6d,0xbf558000,0xbe483f6d,0x3f7bbf35,0xbf0ebec4,
0xbf550000,0xbe483f6d,0x3f7bbf35,0xbf0ebec4,0x3f0ebf80,0xbf7b3ec4,0x3e483f35,0x3f55bf6d,0x3f0ebf80,0xbf7b3ec4,0x3e483f35,0x3f55bf6d,
0x3f558000,0x3e48bf6d,0xbf7b3f35,0x3f0e3ec4,0xbf358000,0xbf353f80,0x3f358000,0x3f35bf80,0xbf353f80,0x3f350000,0x3f35bf80,0xbf350000,
0xbf358000,0xbf353f80,0x3f358000,0x3f35bf80,0xbf353f80,0x3f350000,0x3f35bf80,0xbf350000,0xbf358000,0xbf353f80,0x3f358000,0x3f35bf80,
0xbf353f80,0x3f350000,0x3f35bf80,0xbf350000,0xbf358000,0xbf353f80,0x3f358000,0x3f35bf80,0xbf353f80,0x3f350000,0x3f35bf80,0xbf350000,
0x3f55bf80,0xbe48bec4,0xbf7b3f35,0xbf0e3f6d,0x3f0e8000,0x3f7bbf6d,0x3e48bf35,0xbf553ec4,0x3f0e0000,0x3f7bbf6d,0x3e48bf35,0xbf553ec4,
0xbf553f80,0x3e483ec4,0x3f7bbf35,0x3f0ebf6d,0xbf553f80,0x3e483ec4,0x3f7bbf35,0x3f0ebf6d,0xbf0e8000,0xbf7b3f6d,0xbe483f35,0x3f55bec4,
0xbf0e0000,0xbf7b3f6d,0xbe483f35,0x3f55bec4,0x3f55bf80,0xbe48bec4,0xbf7b3f35,0xbf0e3f6d,0x3ec48000,0x3f6dbf35,0x3f6dbf80,0x3ec4bf35,
0x3f6dbf80,0x3ec4bf35,0xbec40000,0xbf6d3f35,0xbec48000,0xbf6d3f35,0xbf6d3f80,0xbec43f35,0xbf6d3f80,0xbec43f35,0x3ec40000,0x3f6dbf35,
0x3ec48000,0x3f6dbf35,0x3f6dbf80,0x3ec4bf35,0x3f6dbf80,0x3ec4bf35,0xbec40000,0xbf6d3f35,0xbec48000,0xbf6d3f35,0xbf6d3f80,0xbec43f35,
0xbf6d3f80,0xbec43f35,0x3ec40000,0x3f6dbf35,0xbe480000,0xbf0e3ec4,0xbf553f35,0xbf7b3f6d,0x3f7bbf80,0x3f55bf6d,0x3f0ebf35,0x3e48bec4,
0x3f7bbf80,0x3f55bf6d,0x3f0ebf35,0x3e48bec4,0x3e488000,0x3f0ebec4,0x3f55bf35,0x3f7bbf6d,0x3e480000,0x3f0ebec4,0x3f55bf35,0x3f7bbf6d,
0xbf7b3f80,0xbf553f6d,0xbf0e3f35,0xbe483ec4,0xbf7b3f80,0xbf553f6d,0xbf0e3f35,0xbe483ec4,0xbe488000,0xbf0e3ec4,0xbf553f35,0xbf7b3f6d,
0xbf803f80,0xbf803f80,0xbf803f80,0xbf803f80,0x0,0x0,0x0,0x0,0xbf803f80,0xbf803f80,0xbf803f80,0xbf803f80,
0x0,0x0,0x0,0x0,0xbf803f80,0xbf803f80,0xbf803f80,0xbf803f80,0x0,0x0,0x0,0x0,
0xbf803f80,0xbf803f80,0xbf803f80,0xbf803f80,0x0,0x0,0x0,0x0,0xbe480000,0xbf0e3ec4,0xbf553f35,0xbf7b3f6d,
0xbf7b3f80,0xbf553f6d,0xbf0e3f35,0xbe483ec4,0xbf7b3f80,0xbf553f6d,0xbf0e3f35,0xbe483ec4,0x3e480000,0x3f0ebec4,0x3f55bf35,0x3f7bbf6d,
0x3e480000,0x3f0ebec4,0x3f55bf35,0x3f7bbf6d,0x3f7bbf80,0x3f55bf6d,0x3f0ebf35,0x3e48bec4,0x3f7bbf80,0x3f55bf6d,0x3f0ebf35,0x3e48bec4,
0xbe480000,0xbf0e3ec4,0xbf553f35,0xbf7b3f6d,0x3f6dbf80,0x3ec4bf35,0xbec40000,0xbf6d3f35,0x3ec40000,0x3f6dbf35,0x3f6dbf80,0x3ec4bf35,
0xbf6d3f80,0xbec43f35,0x3ec40000,0x3f6dbf35,0xbec40000,0xbf6d3f35,0xbf6d3f80,0xbec43f35,0x3f6dbf80,0x3ec4bf35,0xbec40000,0xbf6d3f35,
0x3ec40000,0x3f6dbf35,0x3f6dbf80,0x3ec4bf35,0xbf6d3f80,0xbec43f35,0x3ec40000,0x3f6dbf35,0xbec40000,0xbf6d3f35,0xbf6d3f80,0xbec43f35,
0x3f55bf80,0xbe48bec4,0xbf7b3f35,0xbf0e3f6d,0xbf0e0000,0xbf7b3f6d,0xbe483f35,0x3f55bec4,0xbf0e0000,0xbf7b3f6d,0xbe483f35,0x3f55bec4,
0xbf553f80,0x3e483ec4,0x3f7bbf35,0x3f0ebf6d,0xbf553f80,0x3e483ec4,0x3f7bbf35,0x3f0ebf6d,0x3f0e0000,0x3f7bbf6d,0x3e48bf35,0xbf553ec4,
0x3f0e0000,0x3f7bbf6d,0x3e48bf35,0xbf553ec4,0x3f55bf80,0xbe48bec4,0xbf7b3f35,0xbf0e3f6d,0xbf353f80,0x3f350000,0x3f35bf80,0xbf350000,
0xbf350000,0xbf353f80,0x3f350000,0x3f35bf80,0xbf353f80,0x3f350000,0x3f35bf80,0xbf350000,0xbf350000,0xbf353f80,0x3f350000,0x3f35bf80,
0xbf353f80,0x3f350000,0x3f35bf80,0xbf350000,0xbf350000,0xbf353f80,0x3f350000,0x3f35bf80,0xbf353f80,0x3f350000,0x3f35bf80,0xbf350000,
0xbf350000,0xbf353f80,0x3f350000,0x3f35bf80,0x3f550000,0x3e48bf6d,0xbf7b3f35,0x3f0e3ec4,0x3f0ebf80,0xbf7b3ec4,0x3e483f35,0x3f55bf6d,
0x3f0ebf80,0xbf7b3ec4,0x3e483f35,0x3f55bf6d,0xbf550000,0xbe483f6d,0x3f7bbf35,0xbf0ebec4,0xbf550000,0xbe483f6d,0x3f7bbf35,0xbf0ebec4,
0xbf0e3f80,0x3f7bbec4,0xbe48bf35,0xbf553f6d,0xbf0e3f80,0x3f7bbec4,0xbe48bf35,0xbf553f6d,0x3f550000,0x3e48bf6d,0xbf7b3f35,0x3f0e3ec4,
0x3ec4bf80,0xbf6d3f35,0x3f6d0000,0xbec4bf35,0x3f6d0000,0xbec4bf35,0xbec43f80,0x3f6dbf35,0xbec43f80,0x3f6dbf35,0xbf6d0000,0x3ec43f35,
0xbf6d0000,0x3ec43f35,0x3ec4bf80,0xbf6d3f35,0x3ec4bf80,0xbf6d3f35,0x3f6d0000,0xbec4bf35,0x3f6d0000,0xbec4bf35,0xbec43f80,0x3f6dbf35,
0xbec43f80,0x3f6dbf35,0xbf6d0000,0x3ec43f35,0xbf6d0000,0x3ec43f35,0x3ec4bf80,0xbf6d3f35,0xbe483f80,0x3f0ebf6d,0xbf553f35,0x3f7bbec4,
0x3f7b0000,0xbf55bec4,0x3f0e3f35,0xbe48bf6d,0x3f7b0000,0xbf55bec4,0x3f0e3f35,0xbe48bf6d,0x3e48bf80,0xbf0e3f6d,0x3f55bf35,0xbf7b3ec4,
0x3e48bf80,0xbf0e3f6d,0x3f55bf35,0xbf7b3ec4,0xbf7b0000,0x3f553ec4,0xbf0ebf35,0x3e483f6d,0xbf7b0000,0x3f553ec4,0xbf0ebf35,0x3e483f6d,
0xbe483f80,0x3f0ebf6d,0xbf553f35,0x3f7bbec4,0x80008000,0x80008000,0x80008000,0x80008000,0xbf803f80,0xbf803f80,0xbf803f80,0xbf803f80,
0x80008000,0x80008000,0x80008000,0x80008000,0xbf803f80,0xbf803f80,0xbf803f80,0xbf803f80,0x80008000,0x80008000,0x80008000,0x80008000,
0xbf803f80,0xbf803f80,0xbf803f80,0xbf803f80,0x80008000,0x80008000,0x80008000,0x80008000,0xbf803f80,0xbf803f80,0xbf803f80,0xbf803f80,
0xbf7b3f80,0xbf553f6d,0xbf0e3f35,0xbe483ec4,0x3e488000,0x3f0ebec4,0x3f55bf35,0x3f7bbf6d,0x3e480000,0x3f0ebec4,0x3f55bf35,0x3f7bbf6d,
0x3f7bbf80,0x3f55bf6d,0x3f0ebf35,0x3e48bec4,0x3f7bbf80,0x3f55bf6d,0x3f0ebf35,0x3e48bec4,0xbe488000,0xbf0e3ec4,0xbf553f35,0xbf7b3f6d,
0xbe480000,0xbf0e3ec4,0xbf553f35,0xbf7b3f6d,0xbf7b3f80,0xbf553f6d,0xbf0e3f35,0xbe483ec4,0xbec48000,0xbf6d3f35,0xbf6d3f80,0xbec43f35,
0x3f6dbf80,0x3ec4bf35,0xbec40000,0xbf6d3f35,0x3ec48000,0x3f6dbf35,0x3f6dbf80,0x3ec4bf35,0xbf6d3f80,0xbec43f35,0x3ec40000,0x3f6dbf35,
0xbec48000,0xbf6d3f35,0xbf6d3f80,0xbec43f35,0x3f6dbf80,0x3ec4bf35,0xbec40000,0xbf6d3f35,0x3ec48000,0x3f6dbf35,0x3f6dbf80,0x3ec4bf35,
0xbf6d3f80,0xbec43f35,0x3ec40000,0x3f6dbf35,0xbf0e0000,0xbf7b3f6d,0xbe483f35,0x3f55bec4,0xbf553f80,0x3e483ec4,0x3f7bbf35,0x3f0ebf6d,
0xbf553f80,0x3e483ec4,0x3f7bbf35,0x3f0ebf6d,0x3f0e8000,0x3f7bbf6d,0x3e48bf35,0xbf553ec4,0x3f0e0000,0x3f7bbf6d,0x3e48bf35,0xbf553ec4,
0x3f55bf80,0xbe48bec4,0xbf7b3f35,0xbf0e3f6d,0x3f55bf80,0xbe48bec4,0xbf7b3f35,0xbf0e3f6d,0xbf0e8000,0xbf7b3f6d,0xbe483f35,0x3f55bec4,
0x3f358000,0x3f35bf80,0xbf358000,0xbf353f80,0xbf353f80,0x3f350000,0x3f35bf80,0xbf350000,0x3f358000,0x3f35bf80,0xbf358000,0xbf353f80,
0xbf353f80,0x3f350000,0x3f35bf80,0xbf350000,0x3f358000,0x3f35bf80,0xbf358000,0xbf353f80,0xbf353f80,0x3f350000,0x3f35bf80,0xbf350000,
0x3f358000,0x3f35bf80,0xbf358000,0xbf353f80,0xbf353f80,0x3f350000,0x3f35bf80,0xbf350000,0x3f0ebf80,0xbf7b3ec4,0x3e483f35,0x3f55bf6d,
0xbf558000,0xbe483f6d,0x3f7bbf35,0xbf0ebec4,0xbf550000,0xbe483f6d,0x3f7bbf35,0xbf0ebec4,0xbf0e3f80,0x3f7bbec4,0xbe48bf35,0xbf553f6d,
0xbf0e3f80,0x3f7bbec4,0xbe48bf35,0xbf553f6d,0x3f558000,0x3e48bf6d,0xbf7b3f35,0x3f0e3ec4,0x3f550000,0x3e48bf6d,0xbf7b3f35,0x3f0e3ec4,
0x3f0ebf80,0xbf7b3ec4,0x3e483f35,0x3f55bf6d,0xbf6d8000,0x3ec43f35,0x3ec4bf80,0xbf6d3f35,0x3ec4bf80,0xbf6d3f35,0x3f6d0000,0xbec4bf35,
0x3f6d8000,0xbec4bf35,0xbec43f80,0x3f6dbf35,0xbec43f80,0x3f6dbf35,0xbf6d0000,0x3ec43f35,0xbf6d8000,0x3ec43f35,0x3ec4bf80,0xbf6d3f35,
0x3ec4bf80,0xbf6d3f35,0x3f6d0000,0xbec4bf35,0x3f6d8000,0xbec4bf35,0xbec43f80,0x3f6dbf35,0xbec43f80,0x3f6dbf35,0xbf6d0000,0x3ec43f35,
0x3f7b0000,0xbf55bec4,0x3f0e3f35,0xbe48bf6d,0x3e48bf80,0xbf0e3f6d,0x3f55bf35,0xbf7b3ec4,0x3e48bf80,0xbf0e3f6d,0x3f55bf35,0xbf7b3ec4,
0xbf7b8000,0x3f553ec4,0xbf0ebf35,0x3e483f6d,0xbf7b0000,0x3f553ec4,0xbf0ebf35,0x3e483f6d,0xbe483f80,0x3f0ebf6d,0xbf553f35,0x3f7bbec4,
0xbe483f80,0x3f0ebf6d,0xbf553f35,0x3f7bbec4,0x3f7b8000,0xbf55bec4,0x3f0e3f35,0xbe48bf6d,0x3f80,0xbf80,0x3f80,0xbf80,
0xbf800000,0x3f800000,0xbf800000,0x3f800000,0x3f80,0xbf80,0x3f80,0xbf80,0xbf800000,0x3f800000,0xbf800000,0x3f800000,
0x3f80,0xbf80,0x3f80,0xbf80,0xbf800000,0x3f800000,0xbf800000,0x3f800000,0x3f80,0xbf80,0x3f80,0xbf80,
0xbf800000,0x3f800000,0xbf800000,0x3f800000,0xbf7b0000,0x3f55bec4,0xbf0e3f35,0x3e48bf6d,0x3e483f80,0xbf0ebf6d,0x3f553f35,0xbf7bbec4,
0x3e483f80,0xbf0ebf6d,0x3f553f35,0xbf7bbec4,0x3f7b0000,0xbf553ec4,0x3f0ebf35,0xbe483f6d,0x3f7b0000,0xbf553ec4,0x3f0ebf35,0xbe483f6d,
0xbe48bf80,0x3f0e3f6d,0xbf55bf35,0x3f7b3ec4,0xbe48bf80,0x3f0e3f6d,0xbf55bf35,0x3f7b3ec4,0xbf7b0000,0x3f55bec4,0xbf0e3f35,0x3e48bf6d,
0xbec4bf80,0x3f6d3f35,0xbf6d0000,0x3ec4bf35,0x3f6d0000,0xbec43f35,0xbec4bf80,0x3f6d3f35,0x3ec43f80,0xbf6dbf35,0x3f6d0000,0xbec43f35,
0xbf6d0000,0x3ec4bf35,0x3ec43f80,0xbf6dbf35,0xbec4bf80,0x3f6d3f35,0xbf6d0000,0x3ec4bf35,0x3f6d0000,0xbec43f35,0xbec4bf80,0x3f6d3f35,
0x3ec43f80,0xbf6dbf35,0x3f6d0000,0xbec43f35,0xbf6d0000,0x3ec4bf35,0x3ec43f80,0xbf6dbf35,0xbf0ebf80,0x3f7b3ec4,0xbe483f35,0xbf55bf6d,
0xbf550000,0xbe48bf6d,0x3f7b3f35,0xbf0e3ec4,0xbf550000,0xbe48bf6d,0x3f7b3f35,0xbf0e3ec4,0x3f0e3f80,0xbf7bbec4,0x3e48bf35,0x3f553f6d,
0x3f0e3f80,0xbf7bbec4,0x3e48bf35,0x3f553f6d,0x3f550000,0x3e483f6d,0xbf7bbf35,0x3f0ebec4,0x3f550000,0x3e483f6d,0xbf7bbf35,0x3f0ebec4,
0xbf0ebf80,0x3f7b3ec4,0xbe483f35,0xbf55bf6d,0x3f353f80,0xbf350000,0xbf35bf80,0x3f350000,0xbf350000,0xbf35bf80,0x3f350000,0x3f353f80,
0x3f353f80,0xbf350000,0xbf35bf80,0x3f350000,0xbf350000,0xbf35bf80,0x3f350000,0x3f353f80,0x3f353f80,0xbf350000,0xbf35bf80,0x3f350000,
0xbf350000,0xbf35bf80,0x3f350000,0x3f353f80,0x3f353f80,0xbf350000,0xbf35bf80,0x3f350000,0xbf350000,0xbf35bf80,0x3f350000,0x3f353f80,
0x3f0e0000,0x3f7b3f6d,0x3e483f35,0xbf55bec4,0xbf55bf80,0x3e48bec4,0x3f7b3f35,0x3f0e3f6d,0xbf55bf80,0x3e48bec4,0x3f7b3f35,0x3f0e3f6d,
0xbf0e0000,0xbf7bbf6d,0xbe48bf35,0x3f553ec4,0xbf0e0000,0xbf7bbf6d,0xbe48bf35,0x3f553ec4,0x3f553f80,0xbe483ec4,0xbf7bbf35,0xbf0ebf6d,
0x3f553f80,0xbe483ec4,0xbf7bbf35,0xbf0ebf6d,0x3f0e0000,0x3f7b3f6d,0x3e483f35,0xbf55bec4,0xbf6dbf80,0xbec4bf35,0x3ec40000,0x3f6d3f35,
0x3ec40000,0x3f6d3f35,0x3f6d3f80,0x3ec43f35,0x3f6d3f80,0x3ec43f35,0xbec40000,0xbf6dbf35,0xbec40000,0xbf6dbf35,0xbf6dbf80,0xbec4bf35,
0xbf6dbf80,0xbec4bf35,0x3ec40000,0x3f6d3f35,0x3ec40000,0x3f6d3f35,0x3f6d3f80,0x3ec43f35,0x3f6d3f80,0x3ec43f35,0xbec40000,0xbf6dbf35,
0xbec40000,0xbf6dbf35,0xbf6dbf80,0xbec4bf35,0x3f7b3f80,0x3f553f6d,0x3f0e3f35,0x3e483ec4,0x3e480000,0x3f0e3ec4,0x3f553f35,0x3f7b3f6d,
0x3e480000,0x3f0e3ec4,0x3f553f35,0x3f7b3f6d,0xbf7bbf80,0xbf55bf6d,0xbf0ebf35,0xbe48bec4,0xbf7bbf80,0xbf55bf6d,0xbf0ebf35,0xbe48bec4,
0xbe480000,0xbf0ebec4,0xbf55bf35,0xbf7bbf6d,0xbe480000,0xbf0ebec4,0xbf55bf35,0xbf7bbf6d,0x3f7b3f80,0x3f553f6d,0x3f0e3f35,0x3e483ec4,
0x3f808000,0xbf808000,0x3f808000,0xbf808000,0x3f80,0xbf80,0x3f80,0xbf80,0x3f808000,0xbf808000,0x3f808000,0xbf808000,
0x3f80,0xbf80,0x3f80,0xbf80,0x3f808000,0xbf808000,0x3f808000,0xbf808000,0x3f80,0xbf80,0x3f80,0xbf80,
0x3f808000,0xbf808000,0x3f808000,0xbf808000,0x3f80,0xbf80,0x3f80,0xbf80,0x3e483f80,0xbf0ebf6d,0x3f553f35,0xbf7bbec4,
0x3f7b8000,0xbf553ec4,0x3f0ebf35,0xbe483f6d,0x3f7b0000,0xbf553ec4,0x3f0ebf35,0xbe483f6d,0xbe48bf80,0x3f0e3f6d,0xbf55bf35,0x3f7b3ec4,
0xbe48bf80,0x3f0e3f6d,0xbf55bf35,0x3f7b3ec4,0xbf7b8000,0x3f55bec4,0xbf0e3f35,0x3e48bf6d,0xbf7b0000,0x3f55bec4,0xbf0e3f35,0x3e48bf6d,
0x3e483f80,0xbf0ebf6d,0x3f553f35,0xbf7bbec4,0xbf6d8000,0x3ec4bf35,0x3ec43f80,0xbf6dbf35,0xbec4bf80,0x3f6d3f35,0xbf6d0000,0x3ec4bf35,
0x3f6d8000,0xbec43f35,0xbec4bf80,0x3f6d3f35,0x3ec43f80,0xbf6dbf35,0x3f6d0000,0xbec43f35,0xbf6d8000,0x3ec4bf35,0x3ec43f80,0xbf6dbf35,
0xbec4bf80,0x3f6d3f35,0xbf6d0000,0x3ec4bf35,0x3f6d8000,0xbec43f35,0xbec4bf80,0x3f6d3f35,0x3ec43f80,0xbf6dbf35,0x3f6d0000,0xbec43f35,
0xbf550000,0xbe48bf6d,0x3f7b3f35,0xbf0e3ec4,0x3f0e3f80,0xbf7bbec4,0x3e48bf35,0x3f553f6d,0x3f0e3f80,0xbf7bbec4,0x3e48bf35,0x3f553f6d,
0x3f558000,0x3e483f6d,0xbf7bbf35,0x3f0ebec4,0x3f550000,0x3e483f6d,0xbf7bbf35,0x3f0ebec4,0xbf0ebf80,0x3f7b3ec4,0xbe483f35,0xbf55bf6d,
0xbf0ebf80,0x3f7b3ec4,0xbe483f35,0xbf55bf6d,0xbf558000,0xbe48bf6d,0x3f7b3f35,0xbf0e3ec4,0x3f358000,0x3f353f80,0xbf358000,0xbf35bf80,
0x3f353f80,0xbf350000,0xbf35bf80,0x3f350000,0x3f358000,0x3f353f80,0xbf358000,0xbf35bf80,0x3f353f80,0xbf350000,0xbf35bf80,0x3f350000,
0x3f358000,0x3f353f80,0xbf358000,0xbf35bf80,0x3f353f80,0xbf350000,0xbf35bf80,0x3f350000,0x3f358000,0x3f353f80,0xbf358000,0xbf35bf80,
0x3f353f80,0xbf350000,0xbf35bf80,0x3f350000,0xbf55bf80,0x3e48bec4,0x3f7b3f35,0x3f0e3f6d,0xbf0e8000,0xbf7bbf6d,0xbe48bf35,0x3f553ec4,
0xbf0e0000,0xbf7bbf6d,0xbe48bf35,0x3f553ec4,0x3f553f80,0xbe483ec4,0xbf7bbf35,0xbf0ebf6d,0x3f553f80,0xbe483ec4,0xbf7bbf35,0xbf0ebf6d,
0x3f0e8000,0x3f7b3f6d,0x3e483f35,0xbf55bec4,0x3f0e0000,0x3f7b3f6d,0x3e483f35,0xbf55bec4,0xbf55bf80,0x3e48bec4,0x3f7b3f35,0x3f0e3f6d,
0xbec48000,0xbf6dbf35,0xbf6dbf80,0xbec4bf35,0xbf6dbf80,0xbec4bf35,0x3ec40000,0x3f6d3f35,0x3ec48000,0x3f6d3f35,0x3f6d3f80,0x3ec43f35,
0x3f6d3f80,0x3ec43f35,0xbec40000,0xbf6dbf35,0xbec48000,0xbf6dbf35,0xbf6dbf80,0xbec4bf35,0xbf6dbf80,0xbec4bf35,0x3ec40000,0x3f6d3f35,
0x3ec48000,0x3f6d3f35,0x3f6d3f80,0x3ec43f35,0x3f6d3f80,0x3ec43f35,0xbec40000,0xbf6dbf35,0x3e480000,0x3f0e3ec4,0x3f553f35,0x3f7b3f6d,
0xbf7bbf80,0xbf55bf6d,0xbf0ebf35,0xbe48bec4,0xbf7bbf80,0xbf55bf6d,0xbf0ebf35,0xbe48bec4,0xbe488000,0xbf0ebec4,0xbf55bf35,0xbf7bbf6d,
0xbe480000,0xbf0ebec4,0xbf55bf35,0xbf7bbf6d,0x3f7b3f80,0x3f553f6d,0x3f0e3f35,0x3e483ec4,0x3f7b3f80,0x3f553f6d,0x3f0e3f35,0x3e483ec4,
0x3e488000,0x3f0e3ec4,0x3f553f35,0x3f7b3f6d,
};
__device__ __align__(1024) uint8_t g_hT[32 * 262144];
__device__ __align__(1024) bf16 g_U[128 * 2 * 8 * 1024];
__device__ __align__(128) float g_gp[128 * 256];
__device__ __align__(128) uint4 g_agg[16 * 512];
#define CS 32
__device__ __align__(128) unsigned g_cnt[8 * 32];
constexpr int CNT_U = 0, CNT_V = 1, CNT_DONE = 2, CNT_EPOCH = 3, CNT_H = 4  ;
#define PROFK(i) do { } while (0)
#define PROFC(i) do { } while (0)
#define PROF(i) do { } while (0)
#define PROFX(i) do { } while (0)
#define PROFR(i) do { } while (0)
#define PROFT(i) do { } while (0)
#define PROFS(i) do { } while (0)
#define PROFG(i) do { } while (0)

constexpr int SLOT = 32768;
constexpr int OFF_HS = 4 * SLOT;
constexpr int OFF_W = OFF_HS + 16384;
constexpr int OFF_F = OFF_W + 2 * 18432;
constexpr int OFF_G = OFF_F + 8192;
constexpr int OFF_K = OFF_G + 1024;
constexpr int OFF_GW = OFF_K + 2048;
constexpr int OFF_U = 6 * SLOT;
constexpr int OFF_BAR = OFF_U + 32768;
constexpr int OFF_SC = OFF_BAR + 320;
constexpr int OFF_KEPT = OFF_SC + 1024;
constexpr int OFF_PROF = OFF_KEPT + 64;
constexpr int SMEM_BYTES = OFF_PROF;
constexpr int BAR_FULL = 0  , BAR_U = 11, BAR_W = 12  , BAR_F = 14  ,
              BAR_EMPTY = 17  , BAR_HW = 22  , BAR_WR = 25, BAR_VW = 26, BAR_S1 = 27,
              BAR_XC = 28  , BAR_HR = 32,
              BAR_C = 34  , BAR_HD = 36  ;

#define DEVI __device__ __forceinline__
constexpr unsigned SPIN_LIMIT = 1u << 22;

DEVI uint32_t smem_u32(const void* p) { return (uint32_t)__cvta_generic_to_shared(p); }
DEVI uint64_t gtime() { uint64_t t; asm volatile("mov.u64 %0, %%globaltimer;" : "=l"(t)); return t; }
DEVI void mbar_init(uint32_t bar, uint32_t cnt) { asm volatile("mbarrier.init.shared::cta.b64 [%0], %1;" :: "r"(bar), "r"(cnt) : "memory"); }
DEVI void mbar_expect_tx(uint32_t bar, uint32_t bytes) { asm volatile("mbarrier.arrive.expect_tx.shared::cta.b64 _, [%0], %1;" :: "r"(bar), "r"(bytes) : "memory"); }
DEVI void mbar_arrive(uint32_t bar) { asm volatile("mbarrier.arrive.shared::cta.b64 _, [%0];" :: "r"(bar) : "memory"); }
#define WAIT_LOOP "{\n.reg .pred p;\n.reg .u32 n;\nmov.u32 n, 0;\n" \
                  "LW:\nmbarrier.try_wait.parity.shared::cta.b64 p, [%0], %1;\n@p bra LD;\n" \
                  "add.u32 n, n, 1;\nsetp.lt.u32 p, n, 131072;\n@p bra LW;\nLD:\n"
DEVI void mbar_wait(uint32_t bar, uint32_t parity) { asm volatile(WAIT_LOOP "}" :: "r"(bar), "r"(parity) : "memory"); }
DEVI void warp_arrive(uint32_t bar) { asm volatile("{\n.reg .pred p;\nelect.sync _|p, 0xffffffff;\n@p mbarrier.arrive.shared::cta.b64 _, [%0];\n}" :: "r"(bar) : "memory"); }
DEVI bool elect() {
    uint32_t p;
    asm volatile("{\n.reg .pred P;\nelect.sync _|P, 0xffffffff;\nselp.u32 %0, 1, 0, P;\n}" : "=r"(p));
    return p;
}
DEVI void fence_barrier_init() { asm volatile("fence.mbarrier_init.release.cluster;" ::: "memory"); }
DEVI void fence_proxy_async_smem() { asm volatile("fence.proxy.async.shared::cta;" ::: "memory"); }
DEVI void helper_sync() { asm volatile("bar.sync 1, 128;" ::: "memory"); }

DEVI void pause(unsigned n) {
    asm volatile("{\n.reg .pred p;\n.reg .u32 a, b;\nmov.u32 a, %%clock;\n"
                 "LP:\nmov.u32 b, %%clock;\nsub.u32 b, b, a;\nsetp.lt.u32 p, b, %0;\n@p bra LP;\n}" :: "r"(n) : "memory");
}
DEVI void sched_fence() { asm volatile("{\n.reg .pred p;\n.reg .b32 n;\nLP:\nactivemask.b32 n;\nsetp.eq.u32 p, n, 0;\n@p bra LP;\n}" ::: "memory"); }
#define P_POLL 0
#define NPOLL 1
DEVI void wait_counter(const unsigned* p, unsigned target) {
    unsigned v[NPOLL];
    auto ld = [&](int i) { asm volatile("ld.relaxed.gpu.global.u32 %0, [%1];" : "=r"(v[i]) : "l"(p) : "memory"); };
#pragma unroll
    for (int i = 0; i < NPOLL; i++) { if (i) pause(200); ld(i); }
#pragma unroll 1
    for (unsigned n = 0; n < SPIN_LIMIT; n++) {
#pragma unroll
        for (int i = 0; i < NPOLL; i++) {
            if ((int)(v[i] - target) >= 0) return;
            if (P_POLL) pause(P_POLL);
            ld(i);
        }
    }
}
DEVI void signal_counter(unsigned* p) {
    asm volatile("red.relaxed.gpu.global.add.u32 [%0], 1;" :: "l"(p) : "memory");
}

DEVI void tma_load_3d(uint32_t dst, const CUtensorMap* map, uint32_t bar, int c0, int c1, int c2) {
    asm volatile("cp.async.bulk.tensor.3d.shared::cluster.global.mbarrier::complete_tx::bytes [%0], [%1, {%3, %4, %5}], [%2];"
        :: "r"(dst), "l"(map), "r"(bar), "r"(c0), "r"(c1), "r"(c2) : "memory");
}
DEVI void tma_load_4d(uint32_t dst, const CUtensorMap* map, uint32_t bar, int c0, int c1, int c2, int c3) {
    asm volatile("cp.async.bulk.tensor.4d.shared::cluster.global.mbarrier::complete_tx::bytes [%0], [%1, {%3, %4, %5, %6}], [%2];"
        :: "r"(dst), "l"(map), "r"(bar), "r"(c0), "r"(c1), "r"(c2), "r"(c3) : "memory");
}
DEVI void tma_load_5d(uint32_t dst, const CUtensorMap* map, uint32_t bar, int c0, int c3, int c4) {
    asm volatile("cp.async.bulk.tensor.5d.shared::cluster.global.mbarrier::complete_tx::bytes [%0], [%1, {%3, %6, %6, %4, %5}], [%2];"
        :: "r"(dst), "l"(map), "r"(bar), "r"(c0), "r"(c3), "r"(c4), "r"(0) : "memory");
}
DEVI void tma_store_4d(const CUtensorMap* map, uint32_t src, int c0, int c1, int c2, int c3) {
    asm volatile("cp.async.bulk.tensor.4d.global.shared::cta.bulk_group [%0, {%2, %3, %4, %5}], [%1];"
        :: "l"(map), "r"(src), "r"(c0), "r"(c1), "r"(c2), "r"(c3) : "memory");
}
DEVI void bulk_load(uint32_t dst, const void* src, uint32_t bytes, uint32_t bar) {
    asm volatile("cp.async.bulk.shared::cluster.global.mbarrier::complete_tx::bytes [%0], [%1], %2, [%3];"
        :: "r"(dst), "l"(src), "r"(bytes), "r"(bar) : "memory");
}
DEVI void bulk_prefetch_l2(const void* src, uint32_t bytes) {
    asm volatile("cp.async.bulk.prefetch.L2.global [%0], %1;" :: "l"(src), "r"(bytes) : "memory");
}
DEVI void tma_store_3d(const CUtensorMap* map, uint32_t src, int c0, int c1, int c2) {
    asm volatile("cp.async.bulk.tensor.3d.global.shared::cta.bulk_group [%0, {%2, %3, %4}], [%1];"
        :: "l"(map), "r"(src), "r"(c0), "r"(c1), "r"(c2) : "memory");
}
DEVI void bulk_store(void* dst, uint32_t src, uint32_t bytes) {
    asm volatile("cp.async.bulk.global.shared::cta.bulk_group [%0], [%1], %2;" :: "l"(dst), "r"(src), "r"(bytes) : "memory");
}
DEVI void bulk_commit() { asm volatile("cp.async.bulk.commit_group;" ::: "memory"); }
DEVI void bulk_wait0() { asm volatile("cp.async.bulk.wait_group 0;" ::: "memory"); }

DEVI void wgmma_fence() { asm volatile("wgmma.fence.sync.aligned;" ::: "memory"); }
DEVI void wgmma_commit() { asm volatile("wgmma.commit_group.sync.aligned;" ::: "memory"); }
template<int N> DEVI void wgmma_wait() { asm volatile("wgmma.wait_group.sync.aligned %0;" :: "n"(N) : "memory"); }
template<int N> DEVI void wgmma_wait_all(float (&d)[N]) {
    wgmma_wait<0>();
#pragma unroll
    for (int i = 0; i < N; i++) asm volatile("" : "+f"(d[i]) :: "memory");
}
template<int R> DEVI void reg_alloc() { asm volatile("setmaxnreg.inc.sync.aligned.u32 %0;" :: "n"(R)); }
template<int R> DEVI void reg_dealloc() { asm volatile("setmaxnreg.dec.sync.aligned.u32 %0;" :: "n"(R)); }

constexpr uint32_t SB0 = 1024;
DEVI uint64_t make_desc(uint32_t off, uint32_t lbo, uint32_t sbo, uint32_t mode = 1) {
    return (uint64_t)(((SB0 + off) >> 4) | ((lbo >> 4) << 16)) | ((uint64_t)((sbo >> 4) | (mode << 30)) << 32);
}

#define ACC8(a, o) "+f"(a[o+0]), "+f"(a[o+1]), "+f"(a[o+2]), "+f"(a[o+3]), "+f"(a[o+4]), "+f"(a[o+5]), "+f"(a[o+6]), "+f"(a[o+7])
#define OUT8(a, o) "=f"(a[o+0]), "=f"(a[o+1]), "=f"(a[o+2]), "=f"(a[o+3]), "=f"(a[o+4]), "=f"(a[o+5]), "=f"(a[o+6]), "=f"(a[o+7])
#define ACC32(a, o) ACC8(a, o), ACC8(a, o+8), ACC8(a, o+16), ACC8(a, o+24)

#define SS_N128 "{\n.reg .pred p;\nsetp.ne.b32 p, %66, 0;\n" \
        "wgmma.mma_async.sync.aligned.m64n128k16.f32.bf16.bf16 " \
        "{%0, %1, %2, %3, %4, %5, %6, %7, %8, %9, %10, %11, %12, %13, %14, %15, " \
        "%16, %17, %18, %19, %20, %21, %22, %23, %24, %25, %26, %27, %28, %29, %30, %31, " \
        "%32, %33, %34, %35, %36, %37, %38, %39, %40, %41, %42, %43, %44, %45, %46, %47, " \
        "%48, %49, %50, %51, %52, %53, %54, %55, %56, %57, %58, %59, %60, %61, %62, %63}, " \
        "%64, %65, p, 1, 1, %67, %68;\n}\n"
template<int TA, int TB>
DEVI void wgmma_n128(float (&d)[64], uint64_t da, uint64_t db, int scale_d) {
    asm volatile(SS_N128 : ACC32(d, 0), ACC32(d, 32) : "l"(da), "l"(db), "r"(scale_d), "n"(TA), "n"(TB));
}
DEVI void wgmma_n128_set(float (&d)[64], uint64_t da, uint64_t db) {
    asm volatile(SS_N128 : OUT8(d, 0), OUT8(d, 8), OUT8(d, 16), OUT8(d, 24), OUT8(d, 32), OUT8(d, 40), OUT8(d, 48), OUT8(d, 56) : "l"(da), "l"(db), "n"(0), "n"(0), "n"(1));
}
#define SS_N16 "{\n.reg .pred p;\nsetp.ne.b32 p, 0, 0;\n" \
        "wgmma.mma_async.sync.aligned.m64n16k16.f32.bf16.bf16 " \
        "{%0, %1, %2, %3, %4, %5, %6, %7}, %8, %9, p, 1, 1, %10, 0;\n}\n"
template<int TA> DEVI void wgmma_n16(float* d, uint64_t da, uint64_t db) {
    asm volatile(SS_N16 : OUT8(d, 0) : "l"(da), "l"(db), "n"(TA));
}
#define SS_N8 "{\n.reg .pred p;\nsetp.ne.b32 p, %6, 0;\n" \
        "wgmma.mma_async.sync.aligned.m64n8k16.f32.bf16.bf16 {%0, %1, %2, %3}, %4, %5, p, 1, 1, 0, 0;\n}\n"
DEVI void wgmma_n8(float (&d)[4], uint64_t da, uint64_t db, bool add) {
    if (add) asm volatile(SS_N8 : "+f"(d[0]), "+f"(d[1]), "+f"(d[2]), "+f"(d[3]) : "l"(da), "l"(db), "n"(1));
    else asm volatile(SS_N8 : "=f"(d[0]), "=f"(d[1]), "=f"(d[2]), "=f"(d[3]) : "l"(da), "l"(db), "n"(0));
}
#define RS_N64 "{\n.reg .pred p;\nsetp.ne.b32 p, %37, 0;\n" \
        "wgmma.mma_async.sync.aligned.m64n64k16.f32.bf16.bf16 " \
        "{%0, %1, %2, %3, %4, %5, %6, %7, %8, %9, %10, %11, %12, %13, %14, %15, " \
        "%16, %17, %18, %19, %20, %21, %22, %23, %24, %25, %26, %27, %28, %29, %30, %31}, " \
        "{%32, %33, %34, %35}, %36, p, 1, 1, %38;\n}\n"
template<int SCALE_D, int TB = 0>
DEVI void wgmma_rs_n64(float (&d)[32], const uint32_t (&a)[4], uint64_t db) {
    if (SCALE_D) asm volatile(RS_N64 : ACC32(d, 0) : "r"(a[0]), "r"(a[1]), "r"(a[2]), "r"(a[3]), "l"(db), "n"(1), "n"(TB));
    else asm volatile(RS_N64 : OUT8(d, 0), OUT8(d, 8), OUT8(d, 16), OUT8(d, 24) : "r"(a[0]), "r"(a[1]), "r"(a[2]), "r"(a[3]), "l"(db), "n"(0), "n"(TB));
}
#define SS_N64 "{\n.reg .pred p;\nsetp.ne.b32 p, %34, 0;\n" \
        "wgmma.mma_async.sync.aligned.m64n64k16.f32.bf16.bf16 " \
        "{%0, %1, %2, %3, %4, %5, %6, %7, %8, %9, %10, %11, %12, %13, %14, %15, " \
        "%16, %17, %18, %19, %20, %21, %22, %23, %24, %25, %26, %27, %28, %29, %30, %31}, " \
        "%32, %33, p, 1, 1, 0, 1;\n}\n"
template<int SCALE_D> DEVI void wgmma_ss_n64(float (&d)[32], uint64_t da, uint64_t db) {
    if (SCALE_D) asm volatile(SS_N64 : ACC32(d, 0) : "l"(da), "l"(db), "n"(1));
    else asm volatile(SS_N64 : OUT8(d, 0), OUT8(d, 8), OUT8(d, 16), OUT8(d, 24) : "l"(da), "l"(db), "n"(0));
}
DEVI void ldsm_x4_t(uint32_t (&r)[4], uint32_t addr) {
    asm volatile("ldmatrix.sync.aligned.m8n8.x4.trans.shared.b16 {%0, %1, %2, %3}, [%4];"
        : "=r"(r[0]), "=r"(r[1]), "=r"(r[2]), "=r"(r[3]) : "r"(addr) : "memory");
}
DEVI void ldsm_x4(uint32_t (&r)[4], uint32_t addr) {
    asm volatile("ldmatrix.sync.aligned.m8n8.x4.shared.b16 {%0, %1, %2, %3}, [%4];"
        : "=r"(r[0]), "=r"(r[1]), "=r"(r[2]), "=r"(r[3]) : "r"(addr) : "memory");
}
DEVI void stsm_x4(uint32_t addr, uint32_t r0, uint32_t r1, uint32_t r2, uint32_t r3) {
    asm volatile("stmatrix.sync.aligned.m8n8.x4.shared.b16 [%0], {%1, %2, %3, %4};"
        :: "r"(addr), "r"(r0), "r"(r1), "r"(r2), "r"(r3) : "memory");
}
DEVI void stsm_x4_t(uint32_t addr, uint32_t r0, uint32_t r1, uint32_t r2, uint32_t r3) {
    asm volatile("stmatrix.sync.aligned.m8n8.x4.trans.shared.b16 [%0], {%1, %2, %3, %4};"
        :: "r"(addr), "r"(r0), "r"(r1), "r"(r2), "r"(r3) : "memory");
}
DEVI uint32_t movm(uint32_t a) { uint32_t d; asm volatile("movmatrix.sync.aligned.m8n8.trans.b16 %0, %1;" : "=r"(d) : "r"(a)); return d; }
DEVI uint32_t pack2(float lo, float hi) { uint32_t d; asm("cvt.rn.bf16x2.f32 %0, %1, %2;" : "=r"(d) : "f"(hi), "f"(lo)); return d; }
DEVI float bf_lo(uint32_t v) { return __uint_as_float(v << 16); }
DEVI float bf_hi(uint32_t v) { return __uint_as_float(v & 0xffff0000u); }
DEVI float bf_round(float v) { return __bfloat162float(__float2bfloat16_rn(v)); }
DEVI uint32_t bf_mul2(uint32_t a, uint32_t b) { uint32_t d; asm("mul.rn.bf16x2 %0, %1, %2;" : "=r"(d) : "r"(a), "r"(b)); return d; }
DEVI uint32_t bf_add2(uint32_t a, uint32_t b) { uint32_t d; asm("add.rn.bf16x2 %0, %1, %2;" : "=r"(d) : "r"(a), "r"(b)); return d; }
DEVI uint32_t bf_sub2(uint32_t a, uint32_t b) { uint32_t d; asm("sub.rn.bf16x2 %0, %1, %2;" : "=r"(d) : "r"(a), "r"(b)); return d; }
DEVI uint4 lds128u(uint32_t a) { uint4 v; asm volatile("ld.shared.v4.u32 {%0, %1, %2, %3}, [%4];" : "=r"(v.x), "=r"(v.y), "=r"(v.z), "=r"(v.w) : "r"(a) : "memory"); return v; }
DEVI void sts128u(uint32_t a, uint32_t x, uint32_t y, uint32_t z, uint32_t w) { asm volatile("st.shared.v4.u32 [%0], {%1, %2, %3, %4};" :: "r"(a), "r"(x), "r"(y), "r"(z), "r"(w) : "memory"); }
DEVI uint2 lds64u(uint32_t a) { uint2 v; asm volatile("ld.shared.v2.u32 {%0, %1}, [%2];" : "=r"(v.x), "=r"(v.y) : "r"(a) : "memory"); return v; }
DEVI uint32_t ldg32u(const void* p) { uint32_t v; asm volatile("ld.global.nc.u32 %0, [%1];" : "=r"(v) : "l"(p) : "memory"); return v; }
DEVI void sts64(uint32_t a, float x, float y) { asm volatile("st.shared.v2.f32 [%0], {%1, %2};" :: "r"(a), "f"(x), "f"(y) : "memory"); }
DEVI void sts32(uint32_t a, uint32_t v) { asm volatile("st.shared.u32 [%0], %1;" :: "r"(a), "r"(v) : "memory"); }
DEVI uint32_t lds16(uint32_t a) { uint32_t v; asm volatile("ld.shared.u16 %0, [%1];" : "=r"(v) : "r"(a) : "memory"); return v; }
DEVI void cmul2(uint32_t& x, uint32_t& y, uint32_t c, uint32_t s, uint32_t n) {
    asm("{\n.reg .b32 t, u;\nmul.rn.bf16x2 t, %1, %4;\nmul.rn.bf16x2 u, %1, %2;\n"
        "fma.rn.bf16x2 %1, %0, %3, u;\nfma.rn.bf16x2 %0, %0, %2, t;\n}" : "+r"(x), "+r"(y) : "r"(c), "r"(s), "r"(n));
}
DEVI uint32_t neg2(uint32_t s) { uint32_t n; asm volatile("xor.b32 %0, %1, 0x80008000;" : "=r"(n) : "r"(s)); return n; }
DEVI void cmul2(uint32_t& x, uint32_t& y, uint32_t c, uint32_t s) { cmul2(x, y, c, s, neg2(s)); }
DEVI void cmul2c(uint32_t& x, uint32_t& y, uint32_t c, uint32_t s) { cmul2(x, y, c, neg2(s), s); }
DEVI void sts16(uint32_t a, float v) { asm volatile("st.shared.u16 [%0], %1;" :: "r"(a), "r"(pack2(v, v)) : "memory"); }

DEVI float2 cmul(float2 a, float2 b) { return make_float2(fmaf(a.x, b.x, -a.y * b.y), fmaf(a.x, b.y, a.y * b.x)); }
DEVI float2 cfma(float2 a, float2 b, float2 c) { return make_float2(fmaf(a.x, b.x, fmaf(-a.y, b.y, c.x)), fmaf(a.x, b.y, fmaf(a.y, b.x, c.y))); }

struct Params {
    const bf16 *lam_re, *lam_im, *log_dt, *dskip, *gate_w, *c_re, *c_im, *b_re, *b_im, *x;
    int swapB;
};

#define R8_POLL 8
#define R8B 1
#define SCB 32
#define C0 1
#define R8A 4
DEVI void radix8(uint32_t sb, bool inv, int w, int lane, int bar) {
    const uint64_t dg = make_desc(OFF_G + (inv ? 512 : 0), 128, 256, 0), da = make_desc(OFF_U, 16, 16384);
    float acc[2][64];
    wgmma_fence();
#pragma unroll
    for (int j = 0; j < 8; j++) wgmma_n16<1>(acc[0] + 8 * j, da + 64 * j, dg);
    wgmma_commit();
    sched_fence();
    asm volatile("" : "+r"(lane));
    const int kk = lane & 7, ch = 2 * w + ((lane >> 3) & 1);
    const uint32_t st = sb + OFF_U + (inv ? (lane >> 4) * 16384 + kk * 128 + ((ch ^ kk) << 4)
        : (kk & 1) * 16384 + (kk >> 2) * 2048 + (lane >> 4) * 1024 + (w >> 1) * 128 + ((((kk & 2) * 2 + ((ch & 3) ^ (kk >> 2) ^ (2 * (kk & 1)))) ^ (w >> 1)) << 4));
    uint32_t sa[4];
#pragma unroll
    for (int i = 0; i < 4; i++) { sa[i] = inv ? (st ^ (i << 4)) + i * 1024 : (st ^ (i << 5)) + i * 256; asm volatile("" : "+r"(sa[i])); }
    const int warp = inv;
    sched_fence();
    if (R8A) {
        wgmma_fence();
#pragma unroll
        for (int j = 0; j < R8A; j++) wgmma_n16<1>(acc[1] + 8 * j, da + 64 * (8 + j), dg);
        wgmma_commit();
    }
    PROFC(8);
#pragma unroll
    for (int i = 0; i < 2; i++) {
        if (i || !R8A) wgmma_wait<0>(); else wgmma_wait<1>();
#pragma unroll
        for (int j = 0; j < 64; j++) asm volatile("" : "+f"(acc[i][j]) :: "memory");
        PROFC(9 + 2 * i);
        asm volatile("bar.sync %0, 128;" :: "r"(bar) : "memory");
        if (!i && R8A < 8) wgmma_fence();
#pragma unroll
        for (int j = 0; j < 8; j++) {
            const float* a = acc[i] + 8 * j;
            if (!i && j + R8A < 8) wgmma_n16<1>(acc[1] + 8 * (j + R8A), da + 64 * (8 + j + R8A), dg);
            stsm_x4_t(sa[j & 3] + (2 * i + (j >> 2)) * 4096, pack2(a[0], a[1]), pack2(a[2], a[3]), pack2(a[4], a[5]), pack2(a[6], a[7]));
        }
        if (!i && R8A < 8) wgmma_commit();
        PROFC(10 + 2 * i);
        fence_proxy_async_smem();
        __syncwarp();
        if (inv) warp_arrive(sb + OFF_BAR + 8 * BAR_VW);
    }
}

template<int N> DEVI void c_take(float (&acc)[32], uint32_t (&p)[16]) {
    wgmma_wait<N>();
#pragma unroll
    for (int i = 0; i < 32; i++) asm volatile("" : "+f"(acc[i]) :: "memory");
#pragma unroll
    for (int i = 0; i < 16; i++) p[i] = pack2(acc[2 * i], acc[2 * i + 1]);
}
DEVI uint64_t desc_at(uint64_t d, uint32_t o) { return (d & 0xffffffff00000000ull) | ((uint32_t)d + o); }
DEVI void c_cols(float (&acc)[32], uint64_t df, uint64_t db, int o) {
    wgmma_fence();
    wgmma_ss_n64<0>(acc, df, desc_at(db, o));
#pragma unroll
    for (int s = 1; s < 4; s++) wgmma_ss_n64<1>(acc, df + 2 * s, desc_at(db, o + 256 * s));
    wgmma_commit();
}

DEVI void phase_c(uint32_t sb, int ps, bool rot, int w, int lane) {
    const int warp = ps, bar = 5 + ps;
    PROFC(0);
    const uint32_t rb = sb + OFF_U + ps * 16384;
    const uint64_t df = make_desc(OFF_F, 16, 1024), db = make_desc(OFF_U + ps * 16384, 16, 1024);
    float acc[2][32];
    c_cols(acc[0], df, db, 0);
    c_cols(acc[1], df, db, 128);
    sched_fence();
    asm volatile("" : "+r"(lane));
    const int g = lane & 7, l3 = (lane >> 3) & 1, l4 = lane >> 4;
    uint32_t wf[2][4][4];
    const uint32_t wo = sb + OFF_W + (1 - ps) * 18432 + l4 * 9216 + g * 64 + ((w ^ (g >> 1)) << 4);
    uint32_t wd = wo + l3 * 1152, wm[2] = {wo + 4608 + (((rot ? 4 : 3) - l3) & 3) * 1152, wo + 4608 + ((rot ? 2 : 1) - l3) * 1152};
    uint32_t xa = rb + w * 4096 + l4 * 1024 + g * 128 + (((4 * l3) ^ g) << 4);
    uint32_t oa = rb + (4 * w + (g >> 1)) * 1024 + (1 - l3) * 512 + (((4 * (g & 1) + l4) ^ (4 - 4 * l3) ^ (g >> 1)) << 4);
    auto load_w = [&](int h) {
#pragma unroll
        for (int j = 0; j < 4; j++) ldsm_x4_t(wf[h][j], (j < 2 ? wd + h * 2304 : wm[h]) + (j & 1) * 512);
    };
    uint32_t tw[8][3];
    {
        const float a0 = (float)(8 * w + (lane >> 2)) * 0.0061359231515425649f, q2 = (float)(2 * (lane & 3)), p16 = (float)(16 * ps);
        const float b0 = a0 * (q2 + p16), b1 = a0 * (q2 - p16);
#pragma unroll
        for (int j = 0; j < 4; j++) {
            const float u = fmaf(a0, 8.f * j, j < 2 ? b0 : b1), v = u + a0, su = __sinf(u), sv = __sinf(v);
            tw[j][0] = pack2(__cosf(u), __cosf(v)); tw[j][1] = pack2(-su, -sv); tw[j][2] = pack2(su, sv);
        }
    }
#pragma unroll
    for (int j = 0; j < 4; j++) asm volatile("" : "+r"(tw[j][0]), "+r"(tw[j][1]), "+r"(tw[j][2]));
    asm volatile("" : "+r"(wd), "+r"(wm[0]), "+r"(wm[1]), "+r"(xa), "+r"(oa));
    sched_fence();
    auto twiddle = [&](uint32_t& x, uint32_t& y, int j) { cmul2(x, y, tw[j][0], tw[j][1], tw[j][2]); };
#pragma unroll
    for (int h = 0; h < 2; h++) {
        uint32_t p[16], a[4][4];
        c_take<1>(acc[h], p);
        if (h == 0) PROFC(1);
#pragma unroll
        for (int i = 0; i < 8; i++) {
            twiddle(p[2 * i], p[2 * i + 1], (i & 3) ^ h);
            a[(i & 3) ^ h][i >> 2] = p[2 * i];
            a[(i & 3) ^ h][2 + (i >> 2)] = p[2 * i + 1];
        }
        wgmma_fence();
        wgmma_rs_n64<0>(acc[h], a[0], desc_at(df, 4 * ps));
        wgmma_rs_n64<1>(acc[h], a[1], desc_at(df, 4 * ps + 2));
        wgmma_rs_n64<1>(acc[h], a[2], desc_at(df, 4 - 4 * ps));
        wgmma_rs_n64<1>(acc[h], a[3], desc_at(df, 6 - 4 * ps));
        wgmma_commit();
        load_w(h);
    }
    PROFC(2);
#pragma unroll
    for (int h = 0; h < 2; h++) {
        uint32_t p[16], a[4][4];
        c_take<1>(acc[h], p);
#pragma unroll
        for (int i = 0; i < 8; i++) {
            const int j = i >> 1, r = i & 1;
            if (j < 2) cmul2(p[4 * j + r], p[4 * j + 2 + r], wf[h][j][r], wf[h][j][2 + r]);
            else cmul2c(p[4 * j + r], p[4 * j + 2 + r], wf[h][j][r], wf[h][j][2 + r]);
            a[j][r] = p[4 * j + 2 + r];
            a[j][2 + r] = p[4 * j + r];
        }
        wgmma_fence();
        wgmma_rs_n64<0>(acc[h], a[0], df);
#pragma unroll
        for (int j = 1; j < 4; j++) wgmma_rs_n64<1>(acc[h], a[j], df + 2 * j);
        wgmma_commit();
    }
    PROFC(3);
#pragma unroll
    for (int j = 0; j < 12; j++) tw[4 + j / 3][j % 3] = ps ? tw[(j / 3) ^ 2][j % 3] : tw[j / 3][j % 3];
    uint32_t p[16];
    auto put = [&](int h) {
#pragma unroll
        for (int i = 0; i < 8; i++) twiddle(p[4 * (i >> 1) + (i & 1)], p[4 * (i >> 1) + 2 + (i & 1)], 4 + (i >> 1));
        if (!h) {
#pragma unroll
            for (int i = 0; i < 16; i++) asm volatile("" : "+r"(p[i]) :: "memory");
            asm volatile("bar.sync %0, 128;" :: "r"(bar) : "memory");
        }
#pragma unroll
        for (int j = 0; j < 4; j++) stsm_x4((xa ^ (j << 4)) + h * 2048, p[4 * j], p[4 * j + 1], p[4 * j + 2], p[4 * j + 3]);
        if (h) fence_proxy_async_smem();
    };
    c_take<1>(acc[0], p);
    put(0);
    c_take<0>(acc[1], p);
    if (!ps) put(1);
    else {
        float fin[2][64];
        auto cols = [&](int n) {
            wgmma_fence();
            wgmma_n128_set(fin[n], df, make_desc(OFF_U + n * 16384, 2048, 1024));
#pragma unroll
            for (int s = 1; s < 4; s++) wgmma_n128<0, 1>(fin[n], df + 2 * s, make_desc(OFF_U + n * 16384, 2048, 1024) + 256 * s, 1);
            wgmma_commit();
            sched_fence();
        };
        cols(0);
#pragma unroll
        for (int i = 0; i < 16; i++) asm volatile("" : "+r"(p[i]) :: "memory");
        put(1);
        PROFC(4);
#pragma unroll
        for (int n = 0; n < 2; n++) {
            wgmma_wait_all(fin[n]);
            asm volatile("bar.sync 6, 128;" ::: "memory");
            if (!n) cols(1);
#pragma unroll
            for (int i = 0; i < 8; i++) {
                const int r = i >> 1;
                const float* a = fin[n] + 8 * i;
                stsm_x4((oa ^ ((r ^ (2 * (i & 1))) << 4)) + r * 128 + (n - 1) * 16384, pack2(a[0], a[1]), pack2(a[2], a[3]), pack2(a[4], a[5]), pack2(a[6], a[7]));
            }
        }
        fence_proxy_async_smem();
        asm volatile("bar.sync 6, 128;" ::: "memory");
    }
    PROFC(5);
}

#define P_T 100
#define P_C 300
#define PACE_HA 100
#define PACE_HB 0
#define HN 4
#define PACE_V 100
#define VFIRST 4
#define K_XE 60
#define PACE_H 200
#define T_W0 2000
#define T_XS 2000
#define D_XS 0
#define P_XS 500
#define T_G 0
#define T_BA 1000
#define T_W1 3000
#define P_W 0
#define P_XE 600
#define P_R0 0
#define POL2 0
#define T_B2 4000
#define T_W 5000
#define PACE_U 200
#define PACE_L 0
#define T_FA 0
#define REG_M 216
#define REG_H 72
#define NS 4
#define QM1 36
#define QM2 36
#define SLOT_OF(k) (((k) + 1) % 4)
DEVI void tma_prefetch_4d(const CUtensorMap* map, int c0, int c1, int c2, int c3) {
    asm volatile("cp.async.bulk.prefetch.tensor.4d.L2.global [%0, {%1, %2, %3, %4}];" :: "l"(map), "r"(c0), "r"(c1), "r"(c2), "r"(c3) : "memory");
}
DEVI void bar_sync(int id, int n) { asm volatile("bar.sync %0, %1;" :: "r"(id), "r"(n) : "memory"); }
DEVI void bar_arrive(int id, int n) { asm volatile("bar.arrive %0, %1;" :: "r"(id), "r"(n) : "memory"); }
DEVI uint4 ldg128(const void* p) { uint4 v; asm volatile("ld.global.nc.v4.u32 {%0, %1, %2, %3}, [%4];" : "=r"(v.x), "=r"(v.y), "=r"(v.z), "=r"(v.w) : "l"(p)); return v; }
DEVI uint32_t ldg16(const void* p) { uint32_t v; asm volatile("ld.global.nc.u16 %0, [%1];" : "=r"(v) : "l"(p)); return v; }
DEVI uint32_t bf_fma2(uint32_t a, uint32_t b, uint32_t c) { uint32_t d; asm("fma.rn.bf16x2 %0, %1, %2, %3;" : "=r"(d) : "r"(a), "r"(b), "r"(c)); return d; }
DEVI void bulk_wait_read() { asm volatile("cp.async.bulk.wait_group.read 0;" ::: "memory"); }

DEVI float lds32f(uint32_t a) { float v; asm volatile("ld.shared.f32 %0, [%1];" : "=f"(v) : "r"(a) : "memory"); return v; }
DEVI uint32_t mbar_test(uint32_t bar, uint32_t parity) {
    uint32_t ok;
    asm volatile("{\n.reg .pred p;\nmbarrier.test_wait.parity.shared::cta.b64 p, [%1], %2;\nselp.u32 %0, 1, 0, p;\n}" : "=r"(ok) : "r"(bar), "r"(parity) : "memory");
    return ok;
}
template<int TA> DEVI void ring_steps(float (&acc)[2][64], uint32_t sb, uint32_t fb, int n, int ns, int s, uint32_t ph, int first_bar, int last_bar, int pi) {
    const uint64_t da0 = TA ? make_desc(0, 2048, 256, 3) : make_desc(0, 16, 1024), db0 = make_desc(16384, 16, 1024);
    const uint32_t fe = fb + 8 * ns, de = sb + OFF_BAR + 8 * BAR_EMPTY - fb;
    uint32_t eb = sb + OFF_BAR + 8 * BAR_HR, f = fb + 8 * s;
    uint64_t da = da0 + (uint32_t)(s * 2048), db = db0 + (uint32_t)(s * 2048);
    bool first = true;
    if (TA) PROFT(72);
    mbar_wait(f, ph);
    if (TA) PROFT(73);
    if (first_bar) bar_sync(first_bar, 256);
    if (TA) PROFT(74);
#pragma unroll 1
    for (;;) {
        PROFK(pi++);
        wgmma_fence();
        constexpr int QM = TA ? QM2 : QM1;
#pragma unroll
        for (int j = 0; j < 8; j++) {
            wgmma_n128<TA, 0>(acc[j & 1], da + 512 * (j & 1) + (TA ? 32 : 2) * (j >> 1), db + 2 * (j >> 1), j > 1 || !first);
            if ((QM >> j) & 1) {
                wgmma_commit();
                wgmma_wait<1>();
                if (!(QM & ((1 << j) - 1))) warp_arrive(eb);
                wgmma_fence();
            }
        }
        wgmma_commit();
        first = false;
        if (--n == 0) break;
        eb = f + de;
        f += 8; da += 2048; db += 2048;
        if (f == fe) { f = fb; da = da0; db = db0; ph ^= 1; }
        const uint32_t ok = mbar_test(f, ph);
        wgmma_wait<1>();
        if (!ok) mbar_wait(f, ph);
        __syncwarp();
    }
    if (last_bar) bar_arrive(last_bar, 256);
}

__global__ void __cluster_dims__(2, 1, 1) __launch_bounds__(384, 1)
fused_kernel(const __grid_constant__ CUtensorMap mapB, const __grid_constant__ CUtensorMap mapX,
             const __grid_constant__ CUtensorMap mapXs, const __grid_constant__ CUtensorMap mapU0,
             const __grid_constant__ CUtensorMap mapU2, const __grid_constant__ CUtensorMap mapXe,
             const __grid_constant__ CUtensorMap mapCre, const __grid_constant__ CUtensorMap mapCim,
             const __grid_constant__ CUtensorMap mapV, const __grid_constant__ CUtensorMap mapO,
             const __grid_constant__ CUtensorMap mapWr, const __grid_constant__ CUtensorMap mapWi,
             const __grid_constant__ CUtensorMap mapH,
             const __grid_constant__ Params P) {
    extern __shared__ __align__(1024) uint8_t sm[];
    const uint32_t sb = smem_u32(sm);
    const uint32_t bars = sb + OFF_BAR;
    const unsigned cl = blockIdx.x >> 1;
    const int role = cl < 4 ? 32 + 8 * cl : cl < 36 ? ((cl - 4) & 24) + ((cl - 5) & 7) : cl < 64 ? 33 + (cl - 36) / 7 * 8 + (cl - 30) % 7 : cl;
    const int b = role * 2 + (blockIdx.x & 1), tid = threadIdx.x, warp = __shfl_sync(0xffffffffu, tid >> 5, 0), lane = tid & 31;
    const bool main_cta = b < 128;
    if (b == 129) return;
    const int rp = (b >> 1) & 3, mq = ((b >> 3) & 2) + (b & 1), dt = ((b >> 1) & 4) + (b >> 5), tc = 4 * rp + mq;
    const int cls = b == 128 ? 128 : (b & 31) ? (b & 31) + 64 * (b >> 5) : (b == 64 ? 32 : b == 32 ? 64 : b);
    if (warp != 8 && elect()) {
        if (warp == 11) PROFG(0);
        const int u = warp - (warp > 8);
        if ((sb & 0x3FFFF) != SB0) __trap();
        asm volatile("prefetch.tensormap [%0];" :: "l"(&mapB + 2 + u) : "memory");
        mbar_init(bars + 8 * (5 + u), 1);
        if (!u) mbar_arrive(bars + 8 * (BAR_FULL + 5));
        if (u == 8) sts32(sb + OFF_KEPT + 32, 0);
        mbar_init(bars + 8 * (16 + u), u ? 4 : 1);
        mbar_init(bars + 8 * (27 + u), u < 1 ? 4 : u == 6 ? 8 : (u == 7 || u == 8) ? 64 : 1);
        fence_barrier_init();
        fence_proxy_async_smem();
    }
    __syncwarp();
    const bool real_cls = (cls & 127) == 0;
    const int t = tid & 127;
    auto load_epoch = [&]() {
        unsigned e;
        asm volatile("ld.relaxed.gpu.global.u32 %0, [%1];" : "=r"(e) : "l"(&g_cnt[CNT_EPOCH * CS]));
        return e + 1;
    };
    const int g = lane >> 2, q = lane & 3;

    if (warp < 8) {
        reg_alloc<REG_M>();
        const int wg = warp >> 2, w = warp & 3;
        if (tid == 0) PROFX(94);
        bar_sync(0, 384);
        if (tid == 224) PROFG(8);
        auto kept = [&](int i) { uint64_t v; asm volatile("ld.volatile.shared.u64 %0, [%1];" : "=l"(v) : "r"(sb + OFF_KEPT + 8 * i) : "memory"); return v; };
        const uint32_t fb = bars + 8 * (BAR_FULL + 5 * wg);
        if (wg) {
            {
                const int pp = (dt * 64 + 8 * (t & 64) + (t & 63)) & 1023;
                const uint32_t lr_ = ldg16(P.lam_re + pp), li_ = ldg16(P.lam_im + pp), ld_ = ldg16(P.log_dt + pp);
                const unsigned epoch = load_epoch();
                if (t < 64 && main_cta) g_agg[rp * 2048 + (dt + (t >> 5) * 8) * 128 + lane * 4 + mq] = make_uint4(0u, 0u, 0u, 0u);
                if (t < 4) asm volatile("st.shared.u64 [%0], %1;" :: "r"(sb + OFF_KEPT + 8 * lane),
                    "l"(lane == 0 ? (P.swapB ? 255ull : 127ull) | ((uint64_t)epoch << 32) : lane == 1 ? (uint64_t)g_agg : (uint64_t)&mapB) : "memory");
                const float lr = bf_lo(lr_), li = bf_lo(li_);
                const float dl = bf_round(expf(bf_lo(ld_)));
                const float mag = expf(dl * lr);
                float sn, cs; sincospif(dl * li * 0.31830988618379067f, &sn, &cs);
                const float2 l1 = make_float2(mag * cs, mag * sn);
                const float inv = 1.f / (lr * lr + li * li);
                const float2 cf = cmul(make_float2(l1.x - 1.f, l1.y), make_float2(lr * inv, -li * inv));
                sts128u(sb + OFF_K + 16 * t, __float_as_uint(l1.x), __float_as_uint(P.swapB ? -l1.y : l1.y), __float_as_uint(cf.x), __float_as_uint(cf.y));
                if (tid == 128) PROFX(92);
            }
            {
                const int kk = (t >> 3) & 7, r = t & 7;
                float sn, cs;
                sincospif((float)(((cls + 256 * kk) * r) & 2047) * (1.f / 1024.f), &sn, &cs);
                sn *= 1.f / 1024.f; cs *= 1.f / 1024.f;
                const uint32_t gf = sb + OFF_G + kk * 16 + r * 2, gi = sb + OFF_G + 512 + r * 16 + (kk & 1) * 128 + (kk & 6);
                if (t < 64) {
                    sts16(gf, cs); sts16(gf + 128, real_cls ? 0.f : sn); sts16(gf + 256, -sn); sts16(gf + 384, real_cls ? 0.f : cs);
                    sts16(gi, cs); sts16(gi + 8, -sn); sts16(gi + 256, sn); sts16(gi + 264, cs);
                }
            }
            if (main_cta) {
                uint32_t fa[16][4];
                pause(T_FA);
#pragma unroll
                for (int i = 0; i < 16; i++) {
                    asm volatile("ld.global.nc.L1::no_allocate.v4.u32 {%0, %1, %2, %3}, [%4];" : "=r"(fa[i][0]), "=r"(fa[i][1]), "=r"(fa[i][2]), "=r"(fa[i][3]) : "l"((const uint4*)c_tab + i * 128 + t));
                }
                if (t == 0) PROFX(91);
                const uint32_t ua = sb + OFF_U + (lane >> 4) * 4096 + (8 * w + (lane & 7)) * 128 + ((((lane >> 3) & 1) ^ (lane & 7)) << 4);
                float acc[4][32];
                const uint64_t db = make_desc(OFF_U, 8192, 1024);
                uint32_t x[4][8], y[4][8];
                float gp[4][4];
#pragma unroll
                for (int m = 0; m < 6; m++) {
                    if (m >= 2) {
                        const int n = m - 2;
                        if (m < 5) wgmma_wait<1>(); else wgmma_wait<0>();
#pragma unroll
                        for (int i = 0; i < 32; i++) asm volatile("" : "+f"(acc[n][i]) :: "memory");
                        asm volatile("" : "+f"(gp[n][0]), "+f"(gp[n][2]) :: "memory");
#pragma unroll
                        for (int j = 0; j < 8; j++) { x[n][j] = pack2(acc[n][4 * j], acc[n][4 * j + 1]); y[n][j] = pack2(acc[n][4 * j + 2], acc[n][4 * j + 3]); }
                    }
                    if (m < 4) {
                        mbar_wait(bars + 8 * (BAR_XC + m), 0);
                        if (t == 0 && m == 3) PROF(8);
                        wgmma_fence();
                        wgmma_rs_n64<0, 1>(acc[m], fa[4 * m], db + 512 * m);
#pragma unroll
                        for (int j = 1; j < 4; j++) wgmma_rs_n64<1, 1>(acc[m], fa[4 * m + j], db + 512 * m + 128 * j);
#pragma unroll
                        for (int j = 0; j < 4; j++) wgmma_n8(gp[m], make_desc(OFF_U, 16, 1024) + 512 * m + 2 * j, make_desc(OFF_GW, 16, 1024) + 2 * j, j);
                        wgmma_commit();
                    }
                }
                if (t < 4) {
#pragma unroll
                    for (int j = 0; j < 8; j++) {
                        const uint32_t s0 = bf_add2(x[0][j], x[2][j]), s2 = bf_add2(x[1][j], x[3][j]), ty = bf_sub2(y[1][j], y[3][j]), sy = bf_add2(y[1][j], y[3][j]);
                        const uint32_t b0 = y[0][j], b2 = y[2][j];
                        y[1][j] = bf_sub2(x[3][j], x[1][j]); x[1][j] = bf_sub2(x[0][j], x[2][j]);
                        x[0][j] = bf_add2(s0, s2); y[0][j] = bf_sub2(s0, s2);
                        x[2][j] = bf_add2(b0, ty); y[2][j] = bf_add2(sy, b2) ^ 0x80008000u;
                        x[3][j] = bf_sub2(b0, ty); y[3][j] = bf_sub2(b2, sy);
                    }
                } else {
#pragma unroll
                    for (int j = 0; j < 8; j++) {
                        const uint32_t s0x = bf_add2(x[0][j], x[2][j]), s1x = bf_sub2(x[0][j], x[2][j]), s2x = bf_add2(x[1][j], x[3][j]), tx = bf_sub2(x[1][j], x[3][j]);
                        const uint32_t s0y = bf_add2(y[0][j], y[2][j]), s1y = bf_sub2(y[0][j], y[2][j]), s2y = bf_add2(y[1][j], y[3][j]), ty = bf_sub2(y[1][j], y[3][j]);
                        x[0][j] = bf_add2(s0x, s2x); y[0][j] = bf_add2(s0y, s2y);
                        x[1][j] = bf_add2(s1x, ty); y[1][j] = bf_sub2(s1y, tx);
                        x[2][j] = bf_sub2(s0x, s2x); y[2][j] = bf_sub2(s0y, s2y);
                        x[3][j] = bf_sub2(s1x, ty); y[3][j] = bf_add2(s1y, tx);
                    }
                }
                helper_sync();
                if (q == 0) {
#pragma unroll
                    for (int i = 0; i < 2; i++)
                        sts128u(sb + OFF_GW + (16 * w + 8 * i + g) * 16, __float_as_uint(gp[0][2 * i]), __float_as_uint(gp[1][2 * i]), __float_as_uint(gp[2][2 * i]), __float_as_uint(gp[3][2 * i]));
                }
#pragma unroll
                for (int c = 0; c < 4; c++)
#pragma unroll
                    for (int j = 0; j < 8; j += 2) stsm_x4((ua ^ (j << 4)) + c * 8192, x[c][j], x[c][j + 1], y[c][j], y[c][j + 1]);
                if (t == 0) PROF(21);
            }
            fence_proxy_async_smem();
            __syncwarp();
            warp_arrive(bars + 8 * BAR_S1);
        }
        {
            float acc[2][64];
            float2 lam8[2], lam32[2], lam64[2], wq[2], w4[2], l32q[2], ex[2];
            float2 ag[2][4];
            if (main_cta) {
                ring_steps<0>(acc, sb, fb, 16, 5 - wg, wg * SLOT_OF(16), 0, 2 * wg, 2 + wg, 16 * wg);
                mbar_wait(bars + 8 * BAR_S1, 0);
                const uint4* ap = (const uint4*)kept(1) + (((tc - 1 - q) >> 2) * 2048 + (dt + 8 * wg) * 128 + t);
                const uint64_t k0 = kept(0);
                const uint32_t fl = (uint32_t)k0, tag = ((uint32_t)(k0 >> 32) & 7) | 8;
                const bool swapB = fl & 128;
                float2 lam1[2], coef[2];
#pragma unroll
                for (int i = 0; i < 2; i++) {
                    const uint4 kv = lds128u(sb + OFF_K + (64 * wg + 32 * i + (t >> 2)) * 16);
                    lam1[i] = make_float2(__uint_as_float(kv.x), __uint_as_float(kv.y));
                    coef[i] = make_float2(__uint_as_float(kv.z), __uint_as_float(kv.w));
                    float2 z = cmul(lam1[i], lam1[i]);
                    z = cmul(z, z);
                    lam8[i] = cmul(z, z);
                    z = cmul(lam8[i], lam8[i]);
                    lam32[i] = cmul(z, z); lam64[i] = cmul(lam32[i], lam32[i]);
                    const float2 l128 = cmul(lam64[i], lam64[i]), l256 = cmul(l128, l128), one = make_float2(1.f, 0.f);
                    w4[i] = cmul(l256, l256);
                    wq[i] = cmul(((tc - 1 - q) & 1) ? l128 : one, ((tc - 1 - q) & 2) ? l256 : one);
                    l32q[i] = cmul((q & 1) ? lam32[i] : one, (q & 2) ? lam64[i] : one);
                    asm volatile("" : "+f"(w4[i].x), "+f"(w4[i].y), "+f"(wq[i].x), "+f"(wq[i].y), "+f"(l32q[i].x), "+f"(l32q[i].y));
                }
                sched_fence();
                wgmma_wait_all(acc[0]);
#pragma unroll
                for (int o = 0; o < 64; o++) asm volatile("" : "+f"(acc[1][o]) :: "memory");
                warp_arrive(bars + 8 * (BAR_EMPTY + SLOT_OF(15)));
                sched_fence();
                if (tid == 0) PROF(3);
                if (tid == 128) PROF(25);
                if (tid == 224) PROFG(12);
                float2 v[2];
#pragma unroll
                for (int c = 0; c < 8; c++) ag[c >> 2][c & 3] = make_float2(acc[c >> 2][16 * (c & 3)], acc[c >> 2][16 * (c & 3) + 2]);
#pragma unroll
                for (int r = 1; r < 8; r++)
#pragma unroll
                    for (int c = 0; c < 8; c++) {
                        const int i = c >> 2, o = 16 * (c & 3) + 4 * (r >> 1) + (r & 1);
                        ag[i][c & 3] = cfma(lam1[i], ag[i][c & 3], make_float2(acc[i][o], acc[i][o + 2]));
                    }
#pragma unroll
                for (int i = 0; i < 2; i++) {
                    v[i] = ag[i][0];
#pragma unroll
                    for (int c = 1; c < 4; c++) v[i] = cfma(lam8[i], v[i], ag[i][c]);
                    float2 n = make_float2(__shfl_up_sync(0xffffffffu, v[i].x, 1, 4), __shfl_up_sync(0xffffffffu, v[i].y, 1, 4));
                    if (q >= 1) v[i] = cfma(lam32[i], n, v[i]);
                    n = make_float2(__shfl_up_sync(0xffffffffu, v[i].x, 2, 4), __shfl_up_sync(0xffffffffu, v[i].y, 2, 4));
                    if (q >= 2) v[i] = cfma(lam64[i], n, v[i]);
                }
                if (q == 3 && tc < 15) {
                    asm volatile("{\n.reg .b64 a, b;\nmov.b64 a, {%1, %2};\nmov.b64 b, {%3, %4};\nst.relaxed.gpu.global.v2.b64 [%0], {a, b};\n}"
                        :: "l"(ap + (2045 + mq)), "r"((__float_as_uint(v[0].x) & ~15u) | tag), "r"(__float_as_uint(v[0].y)),
                           "r"((__float_as_uint(v[1].x) & ~15u) | tag), "r"(__float_as_uint(v[1].y)) : "memory");
                }
                PROFS(72 + 8 * wg);
                sched_fence();
                {
                    float m00[2], m01[2], m10[2], m11[2];
                    auto scale = [&](int i, float& x, float& y) { const float u = fmaf(m00[i], x, m01[i] * y); y = fmaf(m10[i], x, m11[i] * y); x = u; };
#pragma unroll
                    for (int i = 0; i < 2; i++) {
                        ex[i] = make_float2(__shfl_up_sync(0xffffffffu, v[i].x, 1, 4), __shfl_up_sync(0xffffffffu, v[i].y, 1, 4));
                        if (q == 0) ex[i] = make_float2(0.f, 0.f);
                        const float cx = coef[i].x, cy = coef[i].y;
                        m00[i] = cx; m01[i] = -cy; m10[i] = -cy; m11[i] = -cx;
                        if (swapB) { m00[i] = -cy; m01[i] = cx; m10[i] = -cx; m11[i] = -cy; }
                        scale(i, ex[i].x, ex[i].y);
                        scale(i, l32q[i].x, l32q[i].y);
                        if (!swapB) { lam1[i].y = -lam1[i].y; lam8[i].y = -lam8[i].y; }
#pragma unroll
                        for (int o = 0; o < 64; o += 4) {
                            scale(i, acc[i][o], acc[i][o + 2]); scale(i, acc[i][o + 1], acc[i][o + 3]);
                            if ((o + 4) % SCB == 0) {
#pragma unroll
                                for (int u = o + 4 - SCB; u < o + 4; u++) asm volatile("" : "+f"(acc[i][u]));
                                sched_fence();
                            }
                        }
#pragma unroll
                        for (int c = 0; c < 3; c++) scale(i, ag[i][c].x, ag[i][c].y);
                    }
                }
                PROFS(73 + 8 * wg);
                uint4 rr[4];
#pragma unroll
                for (int n = 0; n < 4; n++) rr[n] = make_uint4(tag, 0u, tag, 0u);
                auto poll = [&]() {
#pragma unroll
                    for (int n = 0; n < 4; n++)
                        asm volatile("{\n.reg .b64 a, b;\n.reg .pred p;\nsetp.lt.s32 p, %5, %6;\nmov.b64 a, {%0, %1};\nmov.b64 b, {%2, %3};\n"
                                     "@p ld.relaxed.gpu.global.v2.b64 {a, b}, [%4];\nmov.b64 {%0, %1}, a;\nmov.b64 {%2, %3}, b;\n}"
                            : "+r"(rr[n].x), "+r"(rr[n].y), "+r"(rr[n].z), "+r"(rr[n].w) : "l"(ap - 2048 * n), "r"(4 * n), "r"(tc - q) : "memory");
                };
                poll();
#pragma unroll 1
                for (unsigned n = 0; n < SPIN_LIMIT; n++) {
                    uint32_t bad = 0;
#pragma unroll
                    for (int j = 0; j < 4; j++) bad |= (rr[j].x ^ tag) | (rr[j].z ^ tag);
                    if (!__any_sync(0xffffffffu, bad & 15)) break;
                    if (n < 3) PROFS(74 + 8 * wg + n);
                    poll();
                }
                float2 part[2] = {make_float2(__uint_as_float(rr[3].x), __uint_as_float(rr[3].y)), make_float2(__uint_as_float(rr[3].z), __uint_as_float(rr[3].w))};
#pragma unroll
                for (int n = 2; n >= 0; n--) {
                    part[0] = cfma(w4[0], part[0], make_float2(__uint_as_float(rr[n].x), __uint_as_float(rr[n].y)));
                    part[1] = cfma(w4[1], part[1], make_float2(__uint_as_float(rr[n].z), __uint_as_float(rr[n].w)));
                }
#pragma unroll
                for (int i = 0; i < 2; i++) {
                    part[i] = cmul(wq[i], part[i]);
                    part[i].x += __shfl_xor_sync(0xffffffffu, part[i].x, 1); part[i].y += __shfl_xor_sync(0xffffffffu, part[i].y, 1);
                    part[i].x += __shfl_xor_sync(0xffffffffu, part[i].x, 2); part[i].y += __shfl_xor_sync(0xffffffffu, part[i].y, 2);
                    if (!swapB) part[i].y = -part[i].y;
                    ex[i] = cfma(l32q[i], part[i], ex[i]);
#pragma unroll
                    for (int c = 0; c < 4; c++) { const float2 n = cfma(lam8[i], ex[i], ag[i][c]); ag[i][c] = ex[i]; ex[i] = n; }
                }
                if (t == 0) PROF(4 + 25 * wg);
                const uint32_t hs = sb + OFF_HS + (lane >> 4) * 1024 + w * 256 + (lane & 7) * 32 + (((lane << 1) ^ (lane << 2)) & 16);
#pragma unroll
                for (int i = 0; i < 2; i++) {
                    if (fl & (4 << i)) {
#pragma unroll
                        for (int r = 0; r < 8; r++)
#pragma unroll
                            for (int c = 0; c < 4; c++) {
                                const int o = 16 * c + 4 * (r >> 1) + (r & 1);
                                ag[i][c] = cfma(lam1[i], ag[i][c], make_float2(acc[i][o], acc[i][o + 2]));
                                acc[i][o] = ag[i][c].x; acc[i][o + 2] = ag[i][c].y;
                            }
                    }
                    if (i) {
                        fence_proxy_async_smem();
                        __syncwarp();
                        warp_arrive(bars + 8 * BAR_HW);
                    }
                    mbar_wait(bars + 8 * (wg ? (i ? BAR_WR : BAR_HD) : BAR_EMPTY + 4), 0);
#pragma unroll
                    for (int z = 0; z < 8; z++) {
                        const float* a = &acc[i][2 * z];
                        stsm_x4(hs + i * (16384 + wg * 18432) + (z & 1) * 8192 + (z >> 1) * 2048, pack2(a[0], a[32]), pack2(a[16], a[48]), pack2(a[1], a[33]), pack2(a[17], a[49]));
                    }
                }
                fence_proxy_async_smem();
                __syncwarp();
                warp_arrive(bars + 8 * (BAR_HW + 1));
                if (t == 0) PROF(5 + 25 * wg);
            } else {
                mbar_wait(bars + 8 * BAR_S1, 0);
            }
        }
        if (wg) mbar_wait(bars + 8 * BAR_WR, 0);
#pragma unroll 1
        for (int ps = wg; ps < 1 + 2 * wg; ps++) {
            if (ps != 1) {
                if (!ps) mbar_wait(bars + 8 * BAR_U, 0);
                if (t == 0) PROF(ps ? 7 : 23);
                radix8(sb, ps, w, lane, 5 + wg);
                if (t == 0) PROF(ps ? 24 : 22);
                if (ps) break;
                bar_sync(5, 128);
            }
            mbar_wait(bars + 8 * (BAR_C + ps), 0);
            phase_c(sb, ps, b + ps == 0, w, lane);
        }
        if (wg == 0) {
            __syncwarp();
            warp_arrive(bars + 8 * BAR_WR);
            if (main_cta) {
                float acc[2][64];
                ring_steps<1>(acc, sb, bars + 8 * BAR_FULL, 31, NS, SLOT_OF(32), 1, 3, 0, 32);
                auto full = [&](int k) { mbar_wait(bars + 8 * (BAR_FULL + SLOT_OF(k)), 1); PROFT(k); };
                auto hstep = [&](int k, int i) {
                    const uint64_t da = make_desc(SLOT_OF(k) * SLOT + i * 8192, 2048, 256, 3), db = make_desc(SLOT_OF(k) * SLOT + 16384, 16, 1024);
                    wgmma_fence();
#pragma unroll
                    for (int j = 0; j < 4; j++) wgmma_n128<1, 0>(acc[i], da + 32 * j, db + 2 * j, 1);
                };
                auto vstep = [&](int k, int i) {
                    const uint64_t da = make_desc(OFF_U - i * 32768 + k * 8192, 16, 1024), db = make_desc(SLOT_OF(64 + (k >> 1)) * SLOT + (k & 1) * 16384, 8192, 1024);
                    if (k || !i) wgmma_fence();
#pragma unroll
                    for (int j = 0; j < 4; j++) wgmma_n128<0, 1>(acc[i], da + 2 * j, db + 128 * j, 1);
                };
                __syncwarp();
                full(63);
                hstep(63, 0);
                bar_sync(4, 256);
                full(64);
                vstep(0, 0);
                vstep(1, 0);
                const CUtensorMap* maps = (const CUtensorMap*)kept(3);
                const uint32_t ob = sb + OFF_U + w * 2048, oa = ob + g * 256 + (((q >> 1) ^ (2 * g & 6)) << 4) + (q & 1) * 8;
#pragma unroll
                for (int i = 0; i < 2; i++) {
                    uint4 e[8];
                    const uint2 sc = lds64u(sb + OFF_SC + (64 * i + 16 * w + 2 * g) * 4);
                    bar_sync(8 + i, 256);
#pragma unroll
                    for (int j = 0; j < 8; j++) e[j] = lds128u(sb + OFF_HS + i * 16384 + (j >> 2) * 8192 + w * 2048 + (j & 3) * 512 + lane * 16);
                    if (i) wgmma_wait<0>();
                    else {
                        full(65);
                        vstep(2, 0);
                        vstep(3, 0);
                        wgmma_commit();
                        hstep(63, 1);
                        vstep(0, 1);
                        wgmma_commit();
                        wgmma_wait<1>();
                    }
#pragma unroll
                    for (int o = 0; o < 64; o++) asm volatile("" : "+f"(acc[i][o]) :: "memory");
                    if (tid == 0) PROF(17 + i);
                    if (tid == 96 && i) PROFG(20);
#pragma unroll
                    for (int c = 0; c < 4; c++) {
#pragma unroll
                        for (int j = 0; j < 8; j++) {
                            const int o = 16 * c + 2 * j;
                            const uint4 e4 = e[2 * c + (j >> 2)];
                            const uint32_t ev = (j & 2) ? ((j & 1) ? e4.w : e4.z) : ((j & 1) ? e4.y : e4.x);
                            const float f = __uint_as_float((j & 1) ? sc.y : sc.x);
                            sts64((oa ^ ((j >> 1) << 5) ^ ((j & 1) * 144)) + c * 8192 - i * 32768, fmaf(f, acc[i][o], bf_lo(ev)), fmaf(f, acc[i][o + 1], bf_hi(ev)));
                        }
                        if (!i && c >= VFIRST && c < 3) {
                            vstep(c + 1, 1);
                            if (c == 2) wgmma_commit();
                        }
                        fence_proxy_async_smem();
                        __syncwarp();
                        if (elect()) tma_store_3d(maps + 9, ob + c * 8192 - i * 32768, 128 * dt + 32 * c, 128 * (tc & 1) + 64 * i + 16 * w, tc >> 1);
                        __syncwarp();
                        if (!i && c < VFIRST && c < 3) {
                            vstep(c + 1, 1);
                            if (c == 2) wgmma_commit();
                        }
                    }
                }
                if (elect()) {
                    bulk_commit();
                    bulk_wait_read();
                }
                if (tid == 0) PROF(19);
                if (tid == 96) { PROF(20); PROFG(4); }
            }
        } else {
            __syncwarp();
            if (tid == 224) PROFG(16);
            if (main_cta) {
                float gs[16];
                uint32_t dk[16], tv[4][4];
#pragma unroll
                for (int j = 0; j < 16; j++) gs[j] = __ldcg(g_gp + (16 * (tc >> 1) + j) * 256 + 128 * (tc & 1) + t);
#pragma unroll
                for (int j = 0; j < 16; j++) dk[j] = ldg32u(P.dskip + 128 * dt + 8 * j + 2 * q);
                const int m0 = ((t >> 2) & 14) + (t >> 6), c0 = 4 * ((t ^ (t >> 3)) & 7);
#pragma unroll
                for (int j = 0; j < 16; j++) {
                    const float a = (float)((j & 3) || c0 ? c0 + (j & 3) : -96) * ((float)(128 * (tc & 1) + 4 * (j & 12) + m0) * 0.024543692606170260f);
                    tv[j >> 2][j & 3] = pack2(__cosf(a), -__sinf(a));
                }
#pragma unroll
                for (int j = 0; j < 4; j++) gs[j] = (gs[j] + gs[j + 4]) + (gs[j + 8] + gs[j + 12]);
                gs[0] = (gs[0] + gs[1]) + (gs[2] + gs[3]);
                const float gg = bf_round(__fdividef(1.f, 1.f + __expf(-bf_round(gs[0])))), og = bf_round(1.f - gg), o2 = fmaxf(2.f * og, 0x1p-40f);
                sts32(sb + OFF_SC + 4 * t, __float_as_uint(o2));
                sts32(sb + OFF_SC + 512 + 4 * t, pack2(__fdividef(gg, o2), og));
                bar_sync(6, 128);
                if (t == 0) PROFX(95);
                auto sign = [](uint32_t n) { return (((n + 1) & 2) << 30) | ((n & 2) << 14); };
                const uint32_t sel = (t & 64) ? 0x1032 : 0x3210;
#pragma unroll
                for (int e = 1; e >= 0; e--) {
                    uint32_t f[4];
#pragma unroll
                    for (int j = 0; j < 4; j++) f[j] = lds16(sb + OFF_SC + 512 + (64 * e + 16 * j + m0) * 4) * 0x10001u;
                    mbar_wait(bars + 8 * (e ? BAR_HD + 1 : BAR_U), !e);
#pragma unroll
                    for (int j = 0; j < 16; j++) {
                        const int k = j & 3, r = j >> 2;
                        uint32_t o[4];
#pragma unroll
                        for (int u = 0; u < 4; u++) {
                            uint32_t v = tv[r][u];
                            if (u == 0 && k < 2 && !c0) v = k ? 0x3f80u : 0x3f003f00u | (t & 64) << 25;
                            if (e) v = ((u & 1) ? __byte_perm(v, 0, 0x1032) : v) ^ sign(u);
                            o[u] = bf_mul2((k & 1) ? __byte_perm(v, 0, sel) : v, f[r] ^ sign(k * m0));
                        }
                        sts128u(sb + OFF_U - e * 32768 + (4 * k + r) * 2048 + t * 16, o[0], o[1], o[2], o[3]);
                    }
                }
                fence_proxy_async_smem();
                bar_arrive(4, 256);
                if (t == 0) PROF(16);
                const uint32_t xa = sb + OFF_HS + (16 * w + (lane & 15)) * 128 + (((lane >> 4) ^ (lane & 7)) << 4);
#pragma unroll
                for (int e = 0; e < 2; e++) {
                    const uint2 u = lds64u(sb + OFF_SC + 512 + (64 * e + 16 * w + 2 * g) * 4);
                    const uint32_t o0 = __byte_perm(u.x, 0, 0x3232), o1 = __byte_perm(u.y, 0, 0x3232);
                    uint32_t x[8][4];
                    mbar_wait(bars + 8 * (BAR_W + e), 1);
#pragma unroll
                    for (int j = 0; j < 8; j++) ldsm_x4(x[j], (xa ^ ((j & 3) << 5)) + e * 16384 + (j >> 2) * 8192);
#pragma unroll
                    for (int j = 0; j < 8; j++) {
#pragma unroll
                        for (int c = 0; c < 4; c++) x[j][c] = bf_mul2(bf_mul2(x[j][c], dk[2 * j + (c >> 1)]), (c & 1) ? o1 : o0);
                        sts128u(sb + OFF_HS + e * 16384 + (j >> 2) * 8192 + w * 2048 + (j & 3) * 512 + lane * 16, x[j][0], x[j][1], x[j][2], x[j][3]);
                    }
                    bar_arrive(8 + e, 256);
                    if (t == 0 && !e) PROF(15);
                }
            }
            if (t == 0) {
                const unsigned old = atomicAdd(&g_cnt[CNT_DONE * CS], 1u);
                if (old == 128) { g_cnt[CNT_DONE * CS] = 0; g_cnt[CNT_EPOCH * CS] = (uint32_t)(kept(0) >> 32); }
            }
        }
    } else {
        reg_dealloc<REG_H>();
        const int w = warp - 8;
        if (w == 0) {
            if (elect()) {
                PROF(0);
#pragma unroll
                for (int i = 0; i < 5; i++) mbar_init(bars + 8 * i, 1);
                fence_barrier_init();
                fence_proxy_async_smem();
                PROFX(88);
            }
            __syncwarp();
            bar_arrive(0, 384);
            if (elect()) {
                if (main_cta) {
#pragma unroll 1
                    for (int k = 0; k < 5; k++) {
                        const uint32_t full = bars + 8 * (BAR_FULL + k), st = sb + k * SLOT;
                        mbar_expect_tx(full, SLOT);
                        tma_load_4d(st, &mapB, full, k * 64, 0, 0, dt * 8);
                        tma_load_4d(st + 16384, &mapX, full, k * 64, 0, 0, tc * 64);
                        if (k == 0) PROFX(89);
                        if (P_R0) pause(P_R0);
                    }
                }
                PROF(27);
            }
            __syncwarp();
            bar_sync(7, 64);
            if (main_cta && elect()) {
                int s = 0; uint32_t ph = 0;
#pragma unroll 1
                for (int k = 5; k < 32; k++) {
                    asm volatile(WAIT_LOOP
                        "cp.async.bulk.tensor.4d.shared::cluster.global.mbarrier::complete_tx::bytes [%3], [%5, {%7, %10, %10, %8}], [%2];\n"
                        "cp.async.bulk.tensor.4d.shared::cluster.global.mbarrier::complete_tx::bytes [%4], [%6, {%7, %10, %10, %9}], [%2];\n"
                        "mbarrier.arrive.expect_tx.shared::cta.b64 _, [%2], 32768;\n}"
                        :: "r"(bars + 8 * (BAR_EMPTY + s)), "r"(ph), "r"(bars + 8 * (BAR_FULL + s + (k >> 4) * 5)), "r"(sb + s * SLOT + 16384), "r"(sb + s * SLOT),
                           "l"(&mapX), "l"(&mapB), "r"((k & 15) * 64), "r"(tc * 64), "r"(dt * 8 + (k >> 4) * 64), "r"(0) : "memory");
                    PROFR(k < 19 ? k - 5 : k - 4);
                    if (++s == (k < 15 ? 5 : NS)) { s = 0; ph ^= 1; }
                }
                auto load_x = [&](int e) {
                    mbar_expect_tx(bars + 8 * (BAR_W + e), 16384);
#pragma unroll
                    for (int i = 0; i < 2; i++) tma_load_5d(sb + OFF_HS + e * 16384 + i * 8192, &mapXe, bars + 8 * (BAR_W + e), 128 * dt + 64 * i, 8 * (tc & 1) + 4 * e, tc >> 1);
                };
                const uint8_t* hp = g_hT + tc * 16384;
#pragma unroll 1
                for (int h = 0; h < 32; h++) {
                    asm volatile("{\n.reg .pred q;\n.reg .u32 v, m;\nld.volatile.shared.u32 v, [%10];\nsetp.gt.u32 q, v, %8;\nmov.u32 m, 0;\n" WAIT_LOOP
                        "cp.async.bulk.tensor.3d.shared::cluster.global.mbarrier::complete_tx::bytes [%3], [%5, {%9, %7, %8}], [%2];\n"
                        "@q bra LH;\nLV:\nld.volatile.shared.u32 v, [%10];\nadd.u32 m, m, 1;\nsetp.le.u32 q, v, %8;\nsetp.lt.and.u32 q, m, 4194304, q;\n@q bra LV;\nLH:\n"
                        "cp.async.bulk.shared::cluster.global.mbarrier::complete_tx::bytes [%4], [%6], 16384, [%2];\n"
                        "mbarrier.arrive.expect_tx.shared::cta.b64 _, [%2], 32768;\n}\n}"
                        :: "r"(bars + 8 * (BAR_EMPTY + s)), "r"(ph), "r"(bars + 8 * (BAR_FULL + s)), "r"(sb + s * SLOT + 16384), "r"(sb + s * SLOT),
                           "l"(&mapCre + (h & 1)), "l"(hp), "r"(dt * 128), "r"(h >> 1), "r"(0), "r"(sb + OFF_KEPT + 32) : "memory");
                    PROFR(h + 28);
                    hp += 16 * 16384;
                    if (h == K_XE - 32) load_x(0);
                    if (++s == NS) { s = 0; ph ^= 1; }
                }
                {
                        mbar_wait(bars + 8 * (BAR_F + 2), 0);
#pragma unroll
                        for (int i = 0; i < 2; i++) {
                            const uint32_t pb = bars + 8 * (BAR_XC + i), full = bars + 8 * (BAR_FULL + SLOT_OF(64 + i)), st = sb + SLOT_OF(64 + i) * SLOT;
                            uint32_t rb;
                            asm("mapa.shared::cluster.u32 %0, %1, %2;" : "=r"(rb) : "r"(pb), "r"(~b & 1));
                            asm volatile(WAIT_LOOP "mbarrier.arrive.shared::cluster.b64 _, [%2];\n}" :: "r"(bars + 8 * (BAR_EMPTY + SLOT_OF(64 + i))), "r"(ph), "r"(rb) : "memory");
                            asm volatile(WAIT_LOOP "cp.async.bulk.tensor.3d.shared::cluster.global.mbarrier::complete_tx::bytes.multicast::cluster [%2], [%3, {%5, %6, %7}], [%4], %8;\n}"
                                :: "r"(pb), "r"(1), "r"(st + (b & 1) * 16384), "l"(&mapV), "r"(full), "r"(0), "r"(i * 128 + (b & 1) * 64), "r"((tc >> 1) * 16 + dt * 2), "h"((uint16_t)3) : "memory");
                            mbar_expect_tx(full, SLOT);
                            PROFR(60 + i);
                        }
                    }
                load_x(1);
            }
        } else {
            const unsigned epoch = load_epoch();
            bar_sync(0, 384);
            if (w == 1) {
                bar_arrive(7, 64);
                if (elect()) {
                    if (main_cta) {
                        pause(T_XS);
                        bulk_load(sb + OFF_GW, P.gate_w + (b & 15) * 64, 128, bars + 8 * BAR_XC);
#pragma unroll 1
                        for (int c = 0; c < 4; c++) {
                            mbar_expect_tx(bars + 8 * (BAR_XC + c), c ? 8192 : 8192 + 128);
                            tma_load_4d(sb + OFF_U + c * 8192, &mapXs, bars + 8 * (BAR_XC + c), (b & 15) * 64, 0, c, b >> 4);
                            pause(P_XS);
                        }
                    }
                    mbar_wait(bars + 8 * BAR_S1, 0);
                    if (main_cta) {
#pragma unroll
                        for (int c = 0; c < 4; c++) {
                            if (c) pause(PACE_U);
                            tma_store_4d(&mapU0, sb + OFF_U + c * 8192, (b & 15) * 64, 32 * c, 0, b >> 4);
                        }
                        bulk_store(g_gp + b * 256, sb + OFF_GW, 1024);
                        bulk_commit();
                        bulk_wait0();
                        signal_counter(&g_cnt[CNT_U * CS]);
                    }
                    PROF(9);
                    mbar_expect_tx(bars + 8 * BAR_U, 32768);
                    wait_counter(&g_cnt[CNT_U * CS], epoch * 128);
                    PROF(11);
#pragma unroll
                    for (int i = 0; i < 8; i++) {
                        if (PACE_L && i && !(i & 1)) pause(PACE_L);
                        tma_load_4d(sb + OFF_U + i * 4096, &mapU2, bars + 8 * BAR_U, 0, 0, (i & 3) * 4, b == 128 ? 1 : b == 0 ? 0 : 2 * b + (i >> 2));
                    }
                    if (main_cta) {
#pragma unroll 1
                        for (int i = 0; i < 2; i++) {
#pragma unroll 1
                            for (int j = 0; j < 2 * HN; j++) {
                                const int hf = j / HN, jj = j % HN;
                                if (jj == 0) mbar_wait(bars + 8 * (BAR_HW + hf), i);
                                if (j) pause(i ? PACE_HB : PACE_HA);
                                tma_store_3d(&mapH, sb + OFF_HS + hf * (16384 + i * 18432) + jj * (16384 / HN), 0, 2 * tc + hf, (dt + 8 * i) * 16 + jj * (16 / HN));
                            }
                            bulk_commit();
                            bulk_wait0();
                            asm volatile("red.relaxed.gpu.global.add.u64 [%0], %1;" :: "l"(&g_cnt[(CNT_H + 2 * i + (tc >> 3)) * CS]), "l"(1ull << (8 * dt)) : "memory");
                            mbar_arrive(bars + 8 * (BAR_HD + i));
                            PROF(i ? 6 : 26);
#pragma unroll 1
                            for (unsigned n = 0; n < SPIN_LIMIT; n++) {
                                uint64_t v;
                                asm volatile("ld.relaxed.gpu.global.u64 %0, [%1];" : "=l"(v) : "l"(&g_cnt[(CNT_H + 2 * i + (tc & 1)) * CS]) : "memory");
                                v = epoch * 0x0808080808080808ull - v;
                                sts32(sb + OFF_KEPT + 32, (__clzll(__brevll(v)) >> 3) + 8 * i);
                                if (!v) break;
                            }
                            PROF(1 + i);
                        }
                    }
                }
            } else {
                const int ld = (1026 * cls) >> 7, lm = (1026 * ((256 - cls) & 255)) >> 7;
                if (elect() && main_cta) {
                    if (w == 3) {
                        pause(T_W);
#pragma unroll 1
                        for (int i = 0; i < 8; i++) {
                            tma_prefetch_4d(&mapWr + (i & 1), 0, (i & 2) ? lm : ld, i >> 2, 0);
                            pause(200);
                        }
                    } else {
                        pause(T_BA + D_XS * tc);
                        if (tc > 4) tma_prefetch_4d(&mapB, tc * 64, 0, 0, dt * 8);
                        pause(T_B2);
                        bulk_prefetch_l2(((b & 1) ? P.b_im : P.b_re) + (64 + (b >> 1)) * 8192, 16384);
                        pause(T_W0 - D_XS * tc);
                    }
                }
#pragma unroll 1
                for (int ps = 0; ps < 2; ps++) {
                    const uint32_t wb = sb + OFF_W + (1 - ps) * 18432;
                    if (w == 2 && elect()) {
                        const uint32_t bw = bars + 8 * (BAR_W + ps);
                        if (ps && main_cta) mbar_wait(bars + 8 * BAR_HD, 0);
                        mbar_expect_tx(bw, ps ? 18432 : 18432 + 8192);
#pragma unroll 1
                        for (int i = 0; i < 4; i++) {
                            tma_load_4d(wb + (i >> 1) * 4608 + (i & 1) * 9216, &mapWr + (i & 1), bw, 0, i < 2 ? ld : lm, (i < 2 || b == 0) ? ps : 1 - ps, 0);
                            pause(P_W);
                        }
                        if (!ps) bulk_load(sb + OFF_F, c_tab + 8192, 8192, bw);
                        PROFX(85 + ps);
                    }
                    if (w == 3 && ps && main_cta && elect()) {
#pragma unroll 1
                        for (int i = 0; i < 8; i++) {
                            bulk_prefetch_l2(((b & 1) ? P.c_im : P.c_re) + (size_t)(b >> 1) * 16384 + i * 2048, 4096);
                            pause(P_C);
                        }
                    }
                    __syncwarp();
                    mbar_wait(bars + 8 * (BAR_W + ps), 0);
                    if (tid == 320) PROF(ps ? 31 : 10);
#pragma unroll 1
                    for (int u = 0; u < 4; u++) {
                        const int row = 2 * (w - 2) + (u >> 1), pl = u & 1;
                        const uint32_t dp = wb + pl * 9216 + row * 1152, mp = wb + pl * 9216 + 4608 + ((b == 0 && ps == 0) ? (4 - row) & 3 : 3 - row) * 1152;
                        const uint32_t od = dp + ((1026 * cls) & 127), om = mp + ((1026 * (256 - cls)) & 127);
                        uint32_t v[4][8], o[4][4];
#pragma unroll
                        for (int i = 0; i < 8; i++) {
                            const uint4 r = lds128u((i < 4 ? (od & ~15u) + 16 * lane + (i >> 1) * 512 : ((om + 1010) & ~15u) - 16 * lane - ((i >> 1) & 1) * 512) + (i & 1) * 16);
                            uint32_t* d = &v[i >> 1][4 * (i & 1)];
                            d[0] = r.x; d[1] = r.y; d[2] = r.z; d[3] = r.w;
                        }
                        const uint32_t e0 = lds16(om), e1 = lds16(od + 1024);
                        auto fwd = [&](int ws) {
#pragma unroll
                            for (int k = 0; k < 8; k++) o[k >> 2][k & 3] = __byte_perm(v[k >> 2][ws + (k & 3)], v[k >> 2][ws + (k & 3) + 1], (cls & 1) ? 0x5432 : 0x3210);
                        };
                        auto mir = [&](int ws) {
#pragma unroll
                            for (int k = 8; k < 16; k++) o[k >> 2][k & 3] = __byte_perm(v[k >> 2][ws + 3 - (k & 3)], v[k >> 2][ws + 4 - (k & 3)], (cls & 1) ? 0x1032 : 0x3254);
                        };
                        switch ((cls >> 1) & 3) { case 0: fwd(0); break; case 1: fwd(1); break; case 2: fwd(2); break; default: fwd(3); }
                        switch (((1 - cls) >> 1) & 3) { case 0: mir(0); break; case 1: mir(1); break; case 2: mir(2); break; default: mir(3); }
                        if (lane == 0) {
                            o[0][0] = pack2(fmaf(pl ? -0.5f : 0.5f, bf_lo(e0), 0.5f * bf_lo(o[0][0])), bf_hi(o[0][0]));
                            o[2][0] = pack2(fmaf(pl ? -0.5f : 0.5f, bf_lo(e1), 0.5f * bf_lo(o[2][0])), bf_hi(o[2][0]));
                        }
                        __syncwarp();
#pragma unroll
                        for (int i = 0; i < 4; i++)
                            sts128u((i < 2 ? dp : mp) + (i & 1) * 512 + ((lane * 16) ^ ((lane << 1) & 48)), o[i][0], o[i][1], o[i][2], o[i][3]);
                    }
                    if (ps) fence_proxy_async_smem();
                    mbar_arrive(bars + 8 * (BAR_C + ps));
                    if (tid == 320) PROF(ps ? 12 : 28);
                }
                if (w == 2 && elect()) {
                    {
#pragma unroll 1
                        for (int i = 0; i < 8; i++) {
                            if (!(i & 3)) mbar_wait(bars + 8 * BAR_VW, i >> 2);
                            else pause(PACE_V);
                            if (!(real_cls && (i & 1))) tma_store_4d(&mapU2, sb + OFF_U + (i & 1) * 16384 + (i >> 1) * 4096, 0, 0, (i >> 1) * 4, b == 128 ? 1 : 2 * b + (i & 1));
                        }
                        bulk_commit();
                        bulk_wait_read();
                        mbar_arrive(bars + 8 * BAR_U);
                        bulk_wait0();
                        signal_counter(&g_cnt[CNT_V * CS]);
                        PROF(13);
                        if (main_cta) {
                            wait_counter(&g_cnt[CNT_V * CS], epoch * 129);
                            mbar_arrive(bars + 8 * (BAR_F + 2));
                            PROF(14);
                        }
                    }
                }
            }
        }
    }
}

typedef CUresult (*PFN_encodeTiled)(CUtensorMap*, CUtensorMapDataType, cuuint32_t, void*, const cuuint64_t*, const cuuint64_t*,
                                    const cuuint32_t*, const cuuint32_t*, CUtensorMapInterleave, CUtensorMapSwizzle,
                                    CUtensorMapL2promotion, CUtensorMapFloatOOBfill);

static CUtensorMap make_map(PFN_encodeTiled enc, const void* ptr, int rank, const cuuint64_t* dims, const cuuint64_t* strides, const cuuint32_t* box,
                            CUtensorMapSwizzle sw = CU_TENSOR_MAP_SWIZZLE_128B, CUtensorMapDataType dt = CU_TENSOR_MAP_DATA_TYPE_BFLOAT16) {
    CUtensorMap m;
    cuuint32_t es[5] = {1, 1, 1, 1, 1};
    enc(&m, dt, rank, (void*)ptr, dims, strides, box, es, CU_TENSOR_MAP_INTERLEAVE_NONE,
        sw, CU_TENSOR_MAP_L2_PROMOTION_L2_128B, CU_TENSOR_MAP_FLOAT_OOB_FILL_NONE);
    return m;
}

extern "C" void kernel_launch(void* const* d_in, const int* in_sizes, int n_in, void* d_out, int out_size) {
    const bf16* x = (const bf16*)d_in[0];
    const bf16* wr = (const bf16*)d_in[1];
    const bf16* wi = (const bf16*)d_in[2];
    const bf16* Bre = (const bf16*)d_in[6];
    const bf16* Bim = (const bf16*)d_in[7];
    const bf16* Cre = (const bf16*)d_in[8];
    const bf16* Cim = (const bf16*)d_in[9];

    void* fn = nullptr;
    cudaDriverEntryPointQueryResult st;
    cudaGetDriverEntryPoint("cuTensorMapEncodeTiled", &fn, cudaEnableDefault, &st);
    PFN_encodeTiled enc = (PFN_encodeTiled)fn;
    void *p_hT, *p_U;
    cudaGetSymbolAddress(&p_hT, g_hT);
    cudaGetSymbolAddress(&p_U, g_U);

    Params P;
    P.lam_re = (const bf16*)d_in[4]; P.lam_im = (const bf16*)d_in[5]; P.log_dt = (const bf16*)d_in[10];
    P.dskip = (const bf16*)d_in[11]; P.gate_w = (const bf16*)d_in[12]; P.c_re = Cre; P.c_im = Cim; P.b_re = Bre; P.b_im = Bim; P.x = x;
    P.swapB = Bim < Bre;

    CUtensorMap mB, mX, mCre, mCim, mXs, mU0, mV, mU2, mXe, mO, mWr, mWi, mH;
    {
        cuuint64_t d[4] = {64, 2052, 2, 4}, s[3] = {128, 262656, 525312};
        cuuint32_t bx[4] = {64, 9, 1, 4};
        mWr = make_map(enc, wr, 4, d, s, bx, CU_TENSOR_MAP_SWIZZLE_NONE);
        mWi = make_map(enc, wi, 4, d, s, bx, CU_TENSOR_MAP_SWIZZLE_NONE);
    }
    {
        cuuint64_t d[3] = {128, 32, 256}, s[2] = {1024, 32768};
        cuuint32_t bx[3] = {128, 1, 16 / HN};
        mH = make_map(enc, p_hT, 3, d, s, bx, CU_TENSOR_MAP_SWIZZLE_NONE, CU_TENSOR_MAP_DATA_TYPE_UINT64);
    }
    {
        const bf16* lo = P.swapB ? Bim : Bre; const bf16* hi = P.swapB ? Bre : Bim;
        cuuint64_t d[4] = {1024, 8, 2, 128}, s[3] = {2048, (cuuint64_t)((const char*)hi - (const char*)lo), 16384};
        cuuint32_t bx[4] = {64, 8, 2, 8};
        mB = make_map(enc, lo, 4, d, s, bx);
    }
    {
        cuuint64_t d[4] = {1024, 2, 4, 976}, s[3] = {2048, 32 * 2048, 2 * 2048};
        cuuint32_t bx[4] = {64, 2, 4, 16};
        mX = make_map(enc, x, 4, d, s, bx);
    }
    {
        cuuint64_t d[3] = {64, 1024, 16}, s[2] = {2048, 128};
        cuuint32_t bx[3] = {64, 128, 1};
        mCre = make_map(enc, Cre, 3, d, s, bx);
        mCim = make_map(enc, Cim, 3, d, s, bx);
    }
    {
        cuuint64_t d[3] = {64, 256, 128}, s[2] = {16384, 128};
        cuuint32_t bx[3] = {64, 64, 2};
        mV = make_map(enc, p_U, 3, d, s, bx);
    }
    {
        cuuint64_t d[5] = {1024, 8, 2, 16, 8}, s[4] = {16 * 2048, 8 * 2048, 128 * 2048, 2048};
        cuuint32_t bx[5] = {64, 8, 2, 4, 1};
        mXe = make_map(enc, x, 5, d, s, bx);
    }
    {
        cuuint64_t d[3] = {1024, 256, 8}, s[2] = {8 * 4096, 4096};
        cuuint32_t bx[3] = {32, 16, 1};
        mO = make_map(enc, d_out, 3, d, s, bx, CU_TENSOR_MAP_SWIZZLE_128B, CU_TENSOR_MAP_DATA_TYPE_FLOAT32);
    }
    {
        cuuint64_t d[4] = {1024, 64, 4, 8}, s[3] = {32 * 2048, 8 * 2048, 2048};
        cuuint32_t bx[4] = {64, 64, 1, 1};
        mXs = make_map(enc, x, 4, d, s, bx);
    }
    {
        cuuint64_t d[4] = {1024, 128, 2, 8}, s[3] = {32768, 16384, 2048};
        cuuint32_t bx[4] = {64, 32, 2, 1};
        mU0 = make_map(enc, p_U, 4, d, s, bx);
    }
    {
        cuuint64_t d[4] = {64, 8, 16, 256}, s[3] = {2048, 128, 16384};
        cuuint32_t bx[4] = {64, 8, 4, 1};
        mU2 = make_map(enc, p_U, 4, d, s, bx);
    }
    cudaFuncSetAttribute(fused_kernel, cudaFuncAttributeMaxDynamicSharedMemorySize, SMEM_BYTES);
    fused_kernel<<<130, 384, SMEM_BYTES, cudaStreamPerThread>>>(mB, mX, mXs, mU0, mU2, mXe, mCre, mCim, mV, mO, mWr, mWi, mH, P);
}
```

```cpp
#include <cuda_runtime.h>
#include <cuda_bf16.h>
#include <cuda.h>
#include <stdint.h>

typedef __nv_bfloat16 bf16;

__device__ const __align__(128) uint32_t c_tab[10240] = {
0x3f803f80,0xbf803f80,0x3f803f80,0xbf803f80,0x3f803f80,0xbf803f80,0x3f803f80,0xbf803f80,0x3f803f80,0xbf803f80,0x3f803f80,0xbf803f80,
0x3f803f80,0xbf803f80,0x3f803f80,0xbf803f80,0x3f7f3f80,0xbdc98000,0x3f223f35,0xbf46bf35,0x3f753f7b,0xbe95be48,0x3ef13f0e,0xbf62bf55,
0x3f623f6d,0xbef1bec4,0x3e953ec4,0xbf75bf6d,0x3f463f55,0xbf22bf0e,0x3dc93e48,0xbf7fbf7b,0x3f7b3f80,0xbe488000,0xbe480000,0xbf7bbf80,
0x3f553f6d,0xbf0ebec4,0xbf0ebec4,0xbf55bf6d,0x3f0e3f35,0xbf55bf35,0xbf55bf35,0xbf0ebf35,0x3e483ec4,0xbf7bbf6d,0xbf7bbf6d,0xbe48bec4,
0x3f753f80,0xbe958000,0xbf62bf35,0xbef1bf35,0x3f223f55,0xbf46bf0e,0xbf7fbf7b,0x3dc9be48,0x3dc93ec4,0xbf7fbf6d,0xbf46bf6d,0x3f223ec4,
0xbef1be48,0xbf62bf7b,0xbe95bf0e,0x3f753f55,0x3f6d3f80,0xbec48000,0xbf6dbf80,0x3ec48000,0x3ec43f35,0xbf6dbf35,0xbec4bf35,0x3f6d3f35,
0xbec40000,0xbf6dbf80,0x3ec40000,0x3f6d3f80,0xbf6dbf35,0xbec4bf35,0x3f6d3f35,0x3ec43f35,0x3f623f80,0xbef18000,0xbe95bf35,0x3f753f35,
0x3dc93f0e,0xbf7fbf55,0x3f223e48,0x3f463f7b,0xbf46bec4,0xbf22bf6d,0x3f7f3f6d,0xbdc93ec4,0xbf75bf7b,0x3e95be48,0x3ef13f55,0xbf62bf0e,
0x3f553f80,0xbf0e8000,0x3f0e0000,0x3f553f80,0xbe483ec4,0xbf7bbf6d,0x3f7b3f6d,0xbe483ec4,0xbf7bbf35,0xbe48bf35,0x3e483f35,0xbf7bbf35,
0xbf0ebf6d,0x3f553ec4,0xbf55bec4,0xbf0ebf6d,0x3f463f80,0xbf228000,0x3f7f3f35,0x3dc93f35,0xbef13e48,0xbf62bf7b,0x3e953f55,0xbf75bf0e,
0xbf75bf6d,0x3e95bec4,0xbf62bec4,0xbef1bf6d,0x3dc9bf0e,0x3f7f3f55,0xbf22bf7b,0x3f463e48,0x3f353f80,0xbf358000,0x3f353f80,0xbf358000,
0xbf350000,0xbf35bf80,0xbf350000,0xbf35bf80,0xbf35bf80,0x3f358000,0xbf35bf80,0x3f358000,0x3f350000,0x3f353f80,0x3f350000,0x3f353f80,
0x3f223f80,0xbf468000,0xbdc93f35,0xbf7fbf35,0xbf62be48,0xbef1bf7b,0xbf75bf55,0x3e95bf0e,0xbe95bf6d,0x3f753ec4,0x3ef1bec4,0x3f623f6d,
0x3f7f3f0e,0x3dc93f55,0x3f463f7b,0xbf223e48,0x3f0e3f80,0xbf558000,0xbf550000,0xbf0ebf80,0xbf7bbec4,0xbe48bf6d,0xbe48bf6d,0x3f7b3ec4,
0x3e48bf35,0x3f7b3f35,0x3f7b3f35,0xbe483f35,0x3f553f6d,0xbf0e3ec4,0xbf0e3ec4,0xbf55bf6d,0x3ef13f80,0xbf628000,0xbf75bf35,0x3e95bf35,
0xbf7fbf0e,0x3dc9bf55,0x3f46be48,0x3f223f7b,0x3f22bec4,0x3f463f6d,0x3dc93f6d,0xbf7fbec4,0x3e953f7b,0xbf75be48,0xbf62bf55,0x3ef1bf0e,
0x3ec43f80,0xbf6d8000,0xbec4bf80,0x3f6d8000,0xbf6dbf35,0x3ec4bf35,0x3f6d3f35,0xbec43f35,0x3f6d0000,0x3ec43f80,0xbf6d0000,0xbec4bf80,
0xbec43f35,0xbf6dbf35,0x3ec4bf35,0x3f6d3f35,0x3e953f80,0xbf758000,0x3ef1bf35,0x3f623f35,0xbf46bf55,0x3f22bf0e,0x3dc93f7b,0xbf7fbe48,
0x3f7f3ec4,0xbdc93f6d,0xbf22bf6d,0x3f46bec4,0xbf623e48,0xbef1bf7b,0x3f753f0e,0xbe953f55,0x3e483f80,0xbf7b8000,0x3f7b0000,0x3e483f80,
0xbf0ebf6d,0x3f55bec4,0xbf553ec4,0xbf0ebf6d,0x3f553f35,0xbf0e3f35,0x3f0ebf35,0x3f553f35,0xbf7bbec4,0x3e48bf6d,0xbe483f6d,0xbf7bbec4,
0x3dc93f80,0xbf7f8000,0x3f463f35,0xbf223f35,0xbe95bf7b,0x3f75be48,0xbf62bf0e,0x3ef1bf55,0x3ef13f6d,0xbf623ec4,0x3f753ec4,0xbe953f6d,
0xbf22bf55,0x3f46bf0e,0xbf7fbe48,0x3dc9bf7b,0x3f80,0xbf808000,0x3f80,0xbf808000,0xbf80,0x3f808000,0xbf80,0x3f808000,
0x3f80,0xbf808000,0x3f80,0xbf808000,0xbf80,0x3f808000,0xbf80,0x3f808000,0xbdc93f80,0xbf7f8000,0xbf463f35,0xbf22bf35,
0x3e95bf7b,0x3f753e48,0x3f62bf0e,0x3ef13f55,0xbef13f6d,0xbf62bec4,0xbf753ec4,0xbe95bf6d,0x3f22bf55,0x3f463f0e,0x3f7fbe48,0x3dc93f7b,
0xbe483f80,0xbf7b8000,0xbf7b0000,0x3e48bf80,0x3f0ebf6d,0x3f553ec4,0x3f553ec4,0xbf0e3f6d,0xbf553f35,0xbf0ebf35,0xbf0ebf35,0x3f55bf35,
0x3f7bbec4,0x3e483f6d,0x3e483f6d,0xbf7b3ec4,0xbe953f80,0xbf758000,0xbef1bf35,0x3f62bf35,0x3f46bf55,0x3f223f0e,0xbdc93f7b,0xbf7f3e48,
0xbf7f3ec4,0xbdc9bf6d,0x3f22bf6d,0x3f463ec4,0x3f623e48,0xbef13f7b,0xbf753f0e,0xbe95bf55,0xbec43f80,0xbf6d8000,0x3ec4bf80,0x3f6d8000,
0x3f6dbf35,0x3ec43f35,0xbf6d3f35,0xbec4bf35,0xbf6d0000,0x3ec4bf80,0x3f6d0000,0xbec43f80,0x3ec43f35,0xbf6d3f35,0xbec4bf35,0x3f6dbf35,
0xbef13f80,0xbf628000,0x3f75bf35,0x3e953f35,0x3f7fbf0e,0x3dc93f55,0xbf46be48,0x3f22bf7b,0xbf22bec4,0x3f46bf6d,0xbdc93f6d,0xbf7f3ec4,
0xbe953f7b,0xbf753e48,0x3f62bf55,0x3ef13f0e,0xbf0e3f80,0xbf558000,0x3f550000,0xbf0e3f80,0x3f7bbec4,0xbe483f6d,0x3e48bf6d,0x3f7bbec4,
0xbe48bf35,0x3f7bbf35,0xbf7b3f35,0xbe48bf35,0xbf553f6d,0xbf0ebec4,0x3f0e3ec4,0xbf553f6d,0xbf223f80,0xbf468000,0x3dc93f35,0xbf7f3f35,
0x3f62be48,0xbef13f7b,0x3f75bf55,0x3e953f0e,0x3e95bf6d,0x3f75bec4,0xbef1bec4,0x3f62bf6d,0xbf7f3f0e,0x3dc9bf55,0xbf463f7b,0xbf22be48,
0xbf353f80,0xbf358000,0xbf353f80,0xbf358000,0x3f350000,0xbf353f80,0x3f350000,0xbf353f80,0x3f35bf80,0x3f358000,0x3f35bf80,0x3f358000,
0xbf350000,0x3f35bf80,0xbf350000,0x3f35bf80,0xbf463f80,0xbf228000,0xbf7f3f35,0x3dc9bf35,0x3ef13e48,0xbf623f7b,0xbe953f55,0xbf753f0e,
0x3f75bf6d,0x3e953ec4,0x3f62bec4,0xbef13f6d,0xbdc9bf0e,0x3f7fbf55,0x3f22bf7b,0x3f46be48,0xbf553f80,0xbf0e8000,0xbf0e0000,0x3f55bf80,
0x3e483ec4,0xbf7b3f6d,0xbf7b3f6d,0xbe48bec4,0x3f7bbf35,0xbe483f35,0xbe483f35,0xbf7b3f35,0x3f0ebf6d,0x3f55bec4,0x3f55bec4,0xbf0e3f6d,
0xbf623f80,0xbef18000,0x3e95bf35,0x3f75bf35,0xbdc93f0e,0xbf7f3f55,0xbf223e48,0x3f46bf7b,0x3f46bec4,0xbf223f6d,0xbf7f3f6d,0xbdc9bec4,
0x3f75bf7b,0x3e953e48,0xbef13f55,0xbf623f0e,0xbf6d3f80,0xbec48000,0x3f6dbf80,0x3ec48000,0xbec43f35,0xbf6d3f35,0x3ec4bf35,0x3f6dbf35,
0x3ec40000,0xbf6d3f80,0xbec40000,0x3f6dbf80,0x3f6dbf35,0xbec43f35,0xbf6d3f35,0x3ec4bf35,0xbf753f80,0xbe958000,0x3f62bf35,0xbef13f35,
0xbf223f55,0xbf463f0e,0x3f7fbf7b,0x3dc93e48,0xbdc93ec4,0xbf7f3f6d,0x3f46bf6d,0x3f22bec4,0x3ef1be48,0xbf623f7b,0x3e95bf0e,0x3f75bf55,
0xbf7b3f80,0xbe488000,0x3e480000,0xbf7b3f80,0xbf553f6d,0xbf0e3ec4,0x3f0ebec4,0xbf553f6d,0xbf0e3f35,0xbf553f35,0x3f55bf35,0xbf0e3f35,
0xbe483ec4,0xbf7b3f6d,0x3f7bbf6d,0xbe483ec4,0xbf7f3f80,0xbdc98000,0xbf223f35,0xbf463f35,0xbf753f7b,0xbe953e48,0xbef13f0e,0xbf623f55,
0xbf623f6d,0xbef13ec4,0xbe953ec4,0xbf753f6d,0xbf463f55,0xbf223f0e,0xbdc93e48,0xbf7f3f7b,0x3f803f80,0xbf803f80,0x3f803f80,0xbf803f80,
0x3f803f80,0xbf803f80,0x3f803f80,0xbf803f80,0x3f803f80,0xbf803f80,0x3f803f80,0xbf803f80,0x3f803f80,0xbf803f80,0x3f803f80,0xbf803f80,
0xbdc90000,0xbf7fbf80,0xbf46bf35,0xbf22bf35,0xbe95be48,0xbf75bf7b,0xbf62bf55,0xbef1bf0e,0xbef1bec4,0xbf62bf6d,0xbf75bf6d,0xbe95bec4,
0xbf22bf0e,0xbf46bf55,0xbf7fbf7b,0xbdc9be48,0xbf7bbf80,0x3e488000,0x3e480000,0x3f7b3f80,0xbf55bf6d,0x3f0e3ec4,0x3f0e3ec4,0x3f553f6d,
0xbf0ebf35,0x3f553f35,0x3f553f35,0x3f0e3f35,0xbe48bec4,0x3f7b3f6d,0x3f7b3f6d,0x3e483ec4,0x3e950000,0x3f753f80,0x3ef13f35,0xbf62bf35,
0x3f463f0e,0x3f223f55,0xbdc93e48,0xbf7fbf7b,0x3f7f3f6d,0x3dc93ec4,0xbf22bec4,0xbf46bf6d,0x3f623f7b,0xbef1be48,0xbf75bf55,0xbe95bf0e,
0x3f6d3f80,0xbec48000,0xbf6dbf80,0x3ec48000,0x3ec43f35,0xbf6dbf35,0xbec4bf35,0x3f6d3f35,0xbec40000,0xbf6dbf80,0x3ec40000,0x3f6d3f80,
0xbf6dbf35,0xbec4bf35,0x3f6d3f35,0x3ec43f35,0xbef10000,0xbf62bf80,0x3f753f35,0x3e953f35,0xbf7fbf55,0xbdc9bf0e,0x3f463f7b,0xbf22be48,
0xbf22bf6d,0x3f463ec4,0xbdc93ec4,0xbf7fbf6d,0x3e95be48,0x3f753f7b,0xbf62bf0e,0xbef1bf55,0xbf55bf80,0x3f0e8000,0xbf0e0000,0xbf55bf80,
0x3e48bec4,0x3f7b3f6d,0xbf7bbf6d,0x3e48bec4,0x3f7b3f35,0x3e483f35,0xbe48bf35,0x3f7b3f35,0x3f0e3f6d,0xbf55bec4,0x3f553ec4,0x3f0e3f6d,
0x3f220000,0x3f463f80,0xbdc9bf35,0x3f7f3f35,0x3f623f7b,0xbef13e48,0x3f753f0e,0x3e953f55,0xbe953ec4,0xbf75bf6d,0x3ef13f6d,0xbf62bec4,
0xbf7fbf55,0x3dc9bf0e,0xbf46be48,0xbf22bf7b,0x3f353f80,0xbf358000,0x3f353f80,0xbf358000,0xbf350000,0xbf35bf80,0xbf350000,0xbf35bf80,
0xbf35bf80,0x3f358000,0xbf35bf80,0x3f358000,0x3f350000,0x3f353f80,0x3f350000,0x3f353f80,0xbf460000,0xbf22bf80,0xbf7fbf35,0x3dc9bf35,
0xbef1bf7b,0x3f623e48,0x3e95bf0e,0x3f753f55,0x3f753ec4,0x3e953f6d,0x3f623f6d,0xbef13ec4,0x3dc93f55,0xbf7fbf0e,0xbf223e48,0xbf46bf7b,
0xbf0ebf80,0x3f558000,0x3f550000,0x3f0e3f80,0x3f7b3ec4,0x3e483f6d,0x3e483f6d,0xbf7bbec4,0xbe483f35,0xbf7bbf35,0xbf7bbf35,0x3e48bf35,
0xbf55bf6d,0x3f0ebec4,0x3f0ebec4,0x3f553f6d,0x3f620000,0x3ef13f80,0xbe953f35,0xbf75bf35,0xbdc93f55,0xbf7fbf0e,0xbf22bf7b,0x3f46be48,
0xbf46bf6d,0x3f22bec4,0x3f7f3ec4,0x3dc93f6d,0x3f753e48,0x3e953f7b,0xbef13f0e,0xbf62bf55,0x3ec43f80,0xbf6d8000,0xbec4bf80,0x3f6d8000,
0xbf6dbf35,0x3ec4bf35,0x3f6d3f35,0xbec43f35,0x3f6d0000,0x3ec43f80,0xbf6d0000,0xbec4bf80,0xbec43f35,0xbf6dbf35,0x3ec4bf35,0x3f6d3f35,
0xbf750000,0xbe95bf80,0x3f623f35,0xbef13f35,0x3f22bf0e,0x3f463f55,0xbf7fbe48,0xbdc9bf7b,0xbdc93f6d,0xbf7fbec4,0x3f46bec4,0x3f223f6d,
0xbef1bf7b,0x3f62be48,0xbe953f55,0xbf75bf0e,0xbe48bf80,0x3f7b8000,0xbf7b0000,0xbe48bf80,0x3f0e3f6d,0xbf553ec4,0x3f55bec4,0x3f0e3f6d,
0xbf55bf35,0x3f0ebf35,0xbf0e3f35,0xbf55bf35,0x3f7b3ec4,0xbe483f6d,0x3e48bf6d,0x3f7b3ec4,0x3f7f0000,0x3dc93f80,0x3f22bf35,0x3f463f35,
0xbf753e48,0xbe95bf7b,0xbef13f55,0xbf62bf0e,0x3f62bec4,0x3ef13f6d,0x3e95bf6d,0x3f753ec4,0xbf463f0e,0xbf22bf55,0xbdc93f7b,0xbf7fbe48,
0x3f80,0xbf808000,0x3f80,0xbf808000,0xbf80,0x3f808000,0xbf80,0x3f808000,0x3f80,0xbf808000,0x3f80,0xbf808000,
0xbf80,0x3f808000,0xbf80,0x3f808000,0xbf7f0000,0x3dc9bf80,0xbf22bf35,0x3f46bf35,0x3f753e48,0xbe953f7b,0x3ef13f55,0xbf623f0e,
0xbf62bec4,0x3ef1bf6d,0xbe95bf6d,0x3f75bec4,0x3f463f0e,0xbf223f55,0x3dc93f7b,0xbf7f3e48,0x3e48bf80,0x3f7b8000,0x3f7b0000,0xbe483f80,
0xbf0e3f6d,0xbf55bec4,0xbf55bec4,0x3f0ebf6d,0x3f55bf35,0x3f0e3f35,0x3f0e3f35,0xbf553f35,0xbf7b3ec4,0xbe48bf6d,0xbe48bf6d,0x3f7bbec4,
0x3f750000,0xbe953f80,0xbf623f35,0xbef1bf35,0xbf22bf0e,0x3f46bf55,0x3f7fbe48,0xbdc93f7b,0x3dc93f6d,0xbf7f3ec4,0xbf46bec4,0x3f22bf6d,
0x3ef1bf7b,0x3f623e48,0x3e953f55,0xbf753f0e,0xbec43f80,0xbf6d8000,0x3ec4bf80,0x3f6d8000,0x3f6dbf35,0x3ec43f35,0xbf6d3f35,0xbec4bf35,
0xbf6d0000,0x3ec4bf80,0x3f6d0000,0xbec43f80,0x3ec43f35,0xbf6d3f35,0xbec4bf35,0x3f6dbf35,0xbf620000,0x3ef1bf80,0x3e953f35,0xbf753f35,
0x3dc93f55,0xbf7f3f0e,0x3f22bf7b,0x3f463e48,0x3f46bf6d,0x3f223ec4,0xbf7f3ec4,0x3dc9bf6d,0xbf753e48,0x3e95bf7b,0x3ef13f0e,0xbf623f55,
0x3f0ebf80,0x3f558000,0xbf550000,0x3f0ebf80,0xbf7b3ec4,0x3e48bf6d,0xbe483f6d,0xbf7b3ec4,0x3e483f35,0xbf7b3f35,0x3f7bbf35,0x3e483f35,
0x3f55bf6d,0x3f0e3ec4,0xbf0ebec4,0x3f55bf6d,0x3f460000,0xbf223f80,0x3f7fbf35,0x3dc93f35,0x3ef1bf7b,0x3f62be48,0xbe95bf0e,0x3f75bf55,
0xbf753ec4,0x3e95bf6d,0xbf623f6d,0xbef1bec4,0xbdc93f55,0xbf7f3f0e,0x3f223e48,0xbf463f7b,0xbf353f80,0xbf358000,0xbf353f80,0xbf358000,
0x3f350000,0xbf353f80,0x3f350000,0xbf353f80,0x3f35bf80,0x3f358000,0x3f35bf80,0x3f358000,0xbf350000,0x3f35bf80,0xbf350000,0x3f35bf80,
0xbf220000,0x3f46bf80,0x3dc9bf35,0x3f7fbf35,0xbf623f7b,0xbef1be48,0xbf753f0e,0x3e95bf55,0x3e953ec4,0xbf753f6d,0xbef13f6d,0xbf623ec4,
0x3f7fbf55,0x3dc93f0e,0x3f46be48,0xbf223f7b,0x3f55bf80,0x3f0e8000,0x3f0e0000,0xbf553f80,0xbe48bec4,0x3f7bbf6d,0x3f7bbf6d,0x3e483ec4,
0xbf7b3f35,0x3e48bf35,0x3e48bf35,0x3f7bbf35,0xbf0e3f6d,0xbf553ec4,0xbf553ec4,0x3f0ebf6d,0x3ef10000,0xbf623f80,0xbf753f35,0x3e95bf35,
0x3f7fbf55,0xbdc93f0e,0xbf463f7b,0xbf223e48,0x3f22bf6d,0x3f46bec4,0x3dc93ec4,0xbf7f3f6d,0xbe95be48,0x3f75bf7b,0x3f62bf0e,0xbef13f55,
0xbf6d3f80,0xbec48000,0x3f6dbf80,0x3ec48000,0xbec43f35,0xbf6d3f35,0x3ec4bf35,0x3f6dbf35,0x3ec40000,0xbf6d3f80,0xbec40000,0x3f6dbf80,
0x3f6dbf35,0xbec43f35,0xbf6d3f35,0x3ec4bf35,0xbe950000,0x3f75bf80,0xbef13f35,0xbf623f35,0xbf463f0e,0x3f22bf55,0x3dc93e48,0xbf7f3f7b,
0xbf7f3f6d,0x3dc9bec4,0x3f22bec4,0xbf463f6d,0xbf623f7b,0xbef13e48,0x3f75bf55,0xbe953f0e,0x3f7bbf80,0x3e488000,0xbe480000,0x3f7bbf80,
0x3f55bf6d,0x3f0ebec4,0xbf0e3ec4,0x3f55bf6d,0x3f0ebf35,0x3f55bf35,0xbf553f35,0x3f0ebf35,0x3e48bec4,0x3f7bbf6d,0xbf7b3f6d,0x3e48bec4,
0x3dc90000,0xbf7f3f80,0x3f46bf35,0xbf223f35,0x3e95be48,0xbf753f7b,0x3f62bf55,0xbef13f0e,0x3ef1bec4,0xbf623f6d,0x3f75bf6d,0xbe953ec4,
0x3f22bf0e,0xbf463f55,0x3f7fbf7b,0xbdc93e48,0x3f803f80,0xbf803f80,0x3f803f80,0xbf803f80,0x3f803f80,0xbf803f80,0x3f803f80,0xbf803f80,
0x3f803f80,0xbf803f80,0x3f803f80,0xbf803f80,0x3f803f80,0xbf803f80,0x3f803f80,0xbf803f80,0xbf7fbf80,0x3dc98000,0xbf22bf35,0x3f463f35,
0xbf75bf7b,0x3e953e48,0xbef1bf0e,0x3f623f55,0xbf62bf6d,0x3ef13ec4,0xbe95bec4,0x3f753f6d,0xbf46bf55,0x3f223f0e,0xbdc9be48,0x3f7f3f7b,
0x3f7b3f80,0xbe488000,0xbe480000,0xbf7bbf80,0x3f553f6d,0xbf0ebec4,0xbf0ebec4,0xbf55bf6d,0x3f0e3f35,0xbf55bf35,0xbf55bf35,0xbf0ebf35,
0x3e483ec4,0xbf7bbf6d,0xbf7bbf6d,0xbe48bec4,0xbf75bf80,0x3e958000,0x3f623f35,0x3ef13f35,0xbf22bf55,0x3f463f0e,0x3f7f3f7b,0xbdc93e48,
0xbdc9bec4,0x3f7f3f6d,0x3f463f6d,0xbf22bec4,0x3ef13e48,0x3f623f7b,0x3e953f0e,0xbf75bf55,0x3f6d3f80,0xbec48000,0xbf6dbf80,0x3ec48000,
0x3ec43f35,0xbf6dbf35,0xbec4bf35,0x3f6d3f35,0xbec40000,0xbf6dbf80,0x3ec40000,0x3f6d3f80,0xbf6dbf35,0xbec4bf35,0x3f6d3f35,0x3ec43f35,
0xbf62bf80,0x3ef18000,0x3e953f35,0xbf75bf35,0xbdc9bf0e,0x3f7f3f55,0xbf22be48,0xbf46bf7b,0x3f463ec4,0x3f223f6d,0xbf7fbf6d,0x3dc9bec4,
0x3f753f7b,0xbe953e48,0xbef1bf55,0x3f623f0e,0x3f553f80,0xbf0e8000,0x3f0e0000,0x3f553f80,0xbe483ec4,0xbf7bbf6d,0x3f7b3f6d,0xbe483ec4,
0xbf7bbf35,0xbe48bf35,0x3e483f35,0xbf7bbf35,0xbf0ebf6d,0x3f553ec4,0xbf55bec4,0xbf0ebf6d,0xbf46bf80,0x3f228000,0xbf7fbf35,0xbdc9bf35,
0x3ef1be48,0x3f623f7b,0xbe95bf55,0x3f753f0e,0x3f753f6d,0xbe953ec4,0x3f623ec4,0x3ef13f6d,0xbdc93f0e,0xbf7fbf55,0x3f223f7b,0xbf46be48,
0x3f353f80,0xbf358000,0x3f353f80,0xbf358000,0xbf350000,0xbf35bf80,0xbf350000,0xbf35bf80,0xbf35bf80,0x3f358000,0xbf35bf80,0x3f358000,
0x3f350000,0x3f353f80,0x3f350000,0x3f353f80,0xbf22bf80,0x3f468000,0x3dc9bf35,0x3f7f3f35,0x3f623e48,0x3ef13f7b,0x3f753f55,0xbe953f0e,
0x3e953f6d,0xbf75bec4,0xbef13ec4,0xbf62bf6d,0xbf7fbf0e,0xbdc9bf55,0xbf46bf7b,0x3f22be48,0x3f0e3f80,0xbf558000,0xbf550000,0xbf0ebf80,
0xbf7bbec4,0xbe48bf6d,0xbe48bf6d,0x3f7b3ec4,0x3e48bf35,0x3f7b3f35,0x3f7b3f35,0xbe483f35,0x3f553f6d,0xbf0e3ec4,0xbf0e3ec4,0xbf55bf6d,
0xbef1bf80,0x3f628000,0x3f753f35,0xbe953f35,0x3f7f3f0e,0xbdc93f55,0xbf463e48,0xbf22bf7b,0xbf223ec4,0xbf46bf6d,0xbdc9bf6d,0x3f7f3ec4,
0xbe95bf7b,0x3f753e48,0x3f623f55,0xbef13f0e,0x3ec43f80,0xbf6d8000,0xbec4bf80,0x3f6d8000,0xbf6dbf35,0x3ec4bf35,0x3f6d3f35,0xbec43f35,
0x3f6d0000,0x3ec43f80,0xbf6d0000,0xbec4bf80,0xbec43f35,0xbf6dbf35,0x3ec4bf35,0x3f6d3f35,0xbe95bf80,0x3f758000,0xbef13f35,0xbf62bf35,
0x3f463f55,0xbf223f0e,0xbdc9bf7b,0x3f7f3e48,0xbf7fbec4,0x3dc9bf6d,0x3f223f6d,0xbf463ec4,0x3f62be48,0x3ef13f7b,0xbf75bf0e,0x3e95bf55,
0x3e483f80,0xbf7b8000,0x3f7b0000,0x3e483f80,0xbf0ebf6d,0x3f55bec4,0xbf553ec4,0xbf0ebf6d,0x3f553f35,0xbf0e3f35,0x3f0ebf35,0x3f553f35,
0xbf7bbec4,0x3e48bf6d,0xbe483f6d,0xbf7bbec4,0xbdc9bf80,0x3f7f8000,0xbf46bf35,0x3f22bf35,0x3e953f7b,0xbf753e48,0x3f623f0e,0xbef13f55,
0xbef1bf6d,0x3f62bec4,0xbf75bec4,0x3e95bf6d,0x3f223f55,0xbf463f0e,0x3f7f3e48,0xbdc93f7b,0x3f80,0xbf808000,0x3f80,0xbf808000,
0xbf80,0x3f808000,0xbf80,0x3f808000,0x3f80,0xbf808000,0x3f80,0xbf808000,0xbf80,0x3f808000,0xbf80,0x3f808000,
0x3dc9bf80,0x3f7f8000,0x3f46bf35,0x3f223f35,0xbe953f7b,0xbf75be48,0xbf623f0e,0xbef1bf55,0x3ef1bf6d,0x3f623ec4,0x3f75bec4,0x3e953f6d,
0xbf223f55,0xbf46bf0e,0xbf7f3e48,0xbdc9bf7b,0xbe483f80,0xbf7b8000,0xbf7b0000,0x3e48bf80,0x3f0ebf6d,0x3f553ec4,0x3f553ec4,0xbf0e3f6d,
0xbf553f35,0xbf0ebf35,0xbf0ebf35,0x3f55bf35,0x3f7bbec4,0x3e483f6d,0x3e483f6d,0xbf7b3ec4,0x3e95bf80,0x3f758000,0x3ef13f35,0xbf623f35,
0xbf463f55,0xbf22bf0e,0x3dc9bf7b,0x3f7fbe48,0x3f7fbec4,0x3dc93f6d,0xbf223f6d,0xbf46bec4,0xbf62be48,0x3ef1bf7b,0x3f75bf0e,0x3e953f55,
0xbec43f80,0xbf6d8000,0x3ec4bf80,0x3f6d8000,0x3f6dbf35,0x3ec43f35,0xbf6d3f35,0xbec4bf35,0xbf6d0000,0x3ec4bf80,0x3f6d0000,0xbec43f80,
0x3ec43f35,0xbf6d3f35,0xbec4bf35,0x3f6dbf35,0x3ef1bf80,0x3f628000,0xbf753f35,0xbe95bf35,0xbf7f3f0e,0xbdc9bf55,0x3f463e48,0xbf223f7b,
0x3f223ec4,0xbf463f6d,0x3dc9bf6d,0x3f7fbec4,0x3e95bf7b,0x3f75be48,0xbf623f55,0xbef1bf0e,0xbf0e3f80,0xbf558000,0x3f550000,0xbf0e3f80,
0x3f7bbec4,0xbe483f6d,0x3e48bf6d,0x3f7bbec4,0xbe48bf35,0x3f7bbf35,0xbf7b3f35,0xbe48bf35,0xbf553f6d,0xbf0ebec4,0x3f0e3ec4,0xbf553f6d,
0x3f22bf80,0x3f468000,0xbdc9bf35,0x3f7fbf35,0xbf623e48,0x3ef1bf7b,0xbf753f55,0xbe95bf0e,0xbe953f6d,0xbf753ec4,0x3ef13ec4,0xbf623f6d,
0x3f7fbf0e,0xbdc93f55,0x3f46bf7b,0x3f223e48,0xbf353f80,0xbf358000,0xbf353f80,0xbf358000,0x3f350000,0xbf353f80,0x3f350000,0xbf353f80,
0x3f35bf80,0x3f358000,0x3f35bf80,0x3f358000,0xbf350000,0x3f35bf80,0xbf350000,0x3f35bf80,0x3f46bf80,0x3f228000,0x3f7fbf35,0xbdc93f35,
0xbef1be48,0x3f62bf7b,0x3e95bf55,0x3f75bf0e,0xbf753f6d,0xbe95bec4,0xbf623ec4,0x3ef1bf6d,0x3dc93f0e,0xbf7f3f55,0xbf223f7b,0xbf463e48,
0xbf553f80,0xbf0e8000,0xbf0e0000,0x3f55bf80,0x3e483ec4,0xbf7b3f6d,0xbf7b3f6d,0xbe48bec4,0x3f7bbf35,0xbe483f35,0xbe483f35,0xbf7b3f35,
0x3f0ebf6d,0x3f55bec4,0x3f55bec4,0xbf0e3f6d,0x3f62bf80,0x3ef18000,0xbe953f35,0xbf753f35,0x3dc9bf0e,0x3f7fbf55,0x3f22be48,0xbf463f7b,
0xbf463ec4,0x3f22bf6d,0x3f7fbf6d,0x3dc93ec4,0xbf753f7b,0xbe95be48,0x3ef1bf55,0x3f62bf0e,0xbf6d3f80,0xbec48000,0x3f6dbf80,0x3ec48000,
0xbec43f35,0xbf6d3f35,0x3ec4bf35,0x3f6dbf35,0x3ec40000,0xbf6d3f80,0xbec40000,0x3f6dbf80,0x3f6dbf35,0xbec43f35,0xbf6d3f35,0x3ec4bf35,
0x3f75bf80,0x3e958000,0xbf623f35,0x3ef1bf35,0x3f22bf55,0x3f46bf0e,0xbf7f3f7b,0xbdc9be48,0x3dc9bec4,0x3f7fbf6d,0xbf463f6d,0xbf223ec4,
0xbef13e48,0x3f62bf7b,0xbe953f0e,0xbf753f55,0xbf7b3f80,0xbe488000,0x3e480000,0xbf7b3f80,0xbf553f6d,0xbf0e3ec4,0x3f0ebec4,0xbf553f6d,
0xbf0e3f35,0xbf553f35,0x3f55bf35,0xbf0e3f35,0xbe483ec4,0xbf7b3f6d,0x3f7bbf6d,0xbe483ec4,0x3f7fbf80,0x3dc98000,0x3f22bf35,0x3f46bf35,
0x3f75bf7b,0x3e95be48,0x3ef1bf0e,0x3f62bf55,0x3f62bf6d,0x3ef1bec4,0x3e95bec4,0x3f75bf6d,0x3f46bf55,0x3f22bf0e,0x3dc9be48,0x3f7fbf7b,
0x3f803f80,0xbf803f80,0x3f803f80,0xbf803f80,0x3f803f80,0xbf803f80,0x3f803f80,0xbf803f80,0x3f803f80,0xbf803f80,0x3f803f80,0xbf803f80,
0x3f803f80,0xbf803f80,0x3f803f80,0xbf803f80,0x3dc90000,0x3f7f3f80,0x3f463f35,0x3f223f35,0x3e953e48,0x3f753f7b,0x3f623f55,0x3ef13f0e,
0x3ef13ec4,0x3f623f6d,0x3f753f6d,0x3e953ec4,0x3f223f0e,0x3f463f55,0x3f7f3f7b,0x3dc93e48,0xbf7bbf80,0x3e488000,0x3e480000,0x3f7b3f80,
0xbf55bf6d,0x3f0e3ec4,0x3f0e3ec4,0x3f553f6d,0xbf0ebf35,0x3f553f35,0x3f553f35,0x3f0e3f35,0xbe48bec4,0x3f7b3f6d,0x3f7b3f6d,0x3e483ec4,
0xbe950000,0xbf75bf80,0xbef1bf35,0x3f623f35,0xbf46bf0e,0xbf22bf55,0x3dc9be48,0x3f7f3f7b,0xbf7fbf6d,0xbdc9bec4,0x3f223ec4,0x3f463f6d,
0xbf62bf7b,0x3ef13e48,0x3f753f55,0x3e953f0e,0x3f6d3f80,0xbec48000,0xbf6dbf80,0x3ec48000,0x3ec43f35,0xbf6dbf35,0xbec4bf35,0x3f6d3f35,
0xbec40000,0xbf6dbf80,0x3ec40000,0x3f6d3f80,0xbf6dbf35,0xbec4bf35,0x3f6d3f35,0x3ec43f35,0x3ef10000,0x3f623f80,0xbf75bf35,0xbe95bf35,
0x3f7f3f55,0x3dc93f0e,0xbf46bf7b,0x3f223e48,0x3f223f6d,0xbf46bec4,0x3dc9bec4,0x3f7f3f6d,0xbe953e48,0xbf75bf7b,0x3f623f0e,0x3ef13f55,
0xbf55bf80,0x3f0e8000,0xbf0e0000,0xbf55bf80,0x3e48bec4,0x3f7b3f6d,0xbf7bbf6d,0x3e48bec4,0x3f7b3f35,0x3e483f35,0xbe48bf35,0x3f7b3f35,
0x3f0e3f6d,0xbf55bec4,0x3f553ec4,0x3f0e3f6d,0xbf220000,0xbf46bf80,0x3dc93f35,0xbf7fbf35,0xbf62bf7b,0x3ef1be48,0xbf75bf0e,0xbe95bf55,
0x3e95bec4,0x3f753f6d,0xbef1bf6d,0x3f623ec4,0x3f7f3f55,0xbdc93f0e,0x3f463e48,0x3f223f7b,0x3f353f80,0xbf358000,0x3f353f80,0xbf358000,
0xbf350000,0xbf35bf80,0xbf350000,0xbf35bf80,0xbf35bf80,0x3f358000,0xbf35bf80,0x3f358000,0x3f350000,0x3f353f80,0x3f350000,0x3f353f80,
0x3f460000,0x3f223f80,0x3f7f3f35,0xbdc93f35,0x3ef13f7b,0xbf62be48,0xbe953f0e,0xbf75bf55,0xbf75bec4,0xbe95bf6d,0xbf62bf6d,0x3ef1bec4,
0xbdc9bf55,0x3f7f3f0e,0x3f22be48,0x3f463f7b,0xbf0ebf80,0x3f558000,0x3f550000,0x3f0e3f80,0x3f7b3ec4,0x3e483f6d,0x3e483f6d,0xbf7bbec4,
0xbe483f35,0xbf7bbf35,0xbf7bbf35,0x3e48bf35,0xbf55bf6d,0x3f0ebec4,0x3f0ebec4,0x3f553f6d,0xbf620000,0xbef1bf80,0x3e95bf35,0x3f753f35,
0x3dc9bf55,0x3f7f3f0e,0x3f223f7b,0xbf463e48,0x3f463f6d,0xbf223ec4,0xbf7fbec4,0xbdc9bf6d,0xbf75be48,0xbe95bf7b,0x3ef1bf0e,0x3f623f55,
0x3ec43f80,0xbf6d8000,0xbec4bf80,0x3f6d8000,0xbf6dbf35,0x3ec4bf35,0x3f6d3f35,0xbec43f35,0x3f6d0000,0x3ec43f80,0xbf6d0000,0xbec4bf80,
0xbec43f35,0xbf6dbf35,0x3ec4bf35,0x3f6d3f35,0x3f750000,0x3e953f80,0xbf62bf35,0x3ef1bf35,0xbf223f0e,0xbf46bf55,0x3f7f3e48,0x3dc93f7b,
0x3dc9bf6d,0x3f7f3ec4,0xbf463ec4,0xbf22bf6d,0x3ef13f7b,0xbf623e48,0x3e95bf55,0x3f753f0e,0xbe48bf80,0x3f7b8000,0xbf7b0000,0xbe48bf80,
0x3f0e3f6d,0xbf553ec4,0x3f55bec4,0x3f0e3f6d,0xbf55bf35,0x3f0ebf35,0xbf0e3f35,0xbf55bf35,0x3f7b3ec4,0xbe483f6d,0x3e48bf6d,0x3f7b3ec4,
0xbf7f0000,0xbdc9bf80,0xbf223f35,0xbf46bf35,0x3f75be48,0x3e953f7b,0x3ef1bf55,0x3f623f0e,0xbf623ec4,0xbef1bf6d,0xbe953f6d,0xbf75bec4,
0x3f46bf0e,0x3f223f55,0x3dc9bf7b,0x3f7f3e48,0x3f80,0xbf808000,0x3f80,0xbf808000,0xbf80,0x3f808000,0xbf80,0x3f808000,
0x3f80,0xbf808000,0x3f80,0xbf808000,0xbf80,0x3f808000,0xbf80,0x3f808000,0x3f7f0000,0xbdc93f80,0x3f223f35,0xbf463f35,
0xbf75be48,0x3e95bf7b,0xbef1bf55,0x3f62bf0e,0x3f623ec4,0xbef13f6d,0x3e953f6d,0xbf753ec4,0xbf46bf0e,0x3f22bf55,0xbdc9bf7b,0x3f7fbe48,
0x3e48bf80,0x3f7b8000,0x3f7b0000,0xbe483f80,0xbf0e3f6d,0xbf55bec4,0xbf55bec4,0x3f0ebf6d,0x3f55bf35,0x3f0e3f35,0x3f0e3f35,0xbf553f35,
0xbf7b3ec4,0xbe48bf6d,0xbe48bf6d,0x3f7bbec4,0xbf750000,0x3e95bf80,0x3f62bf35,0x3ef13f35,0x3f223f0e,0xbf463f55,0xbf7f3e48,0x3dc9bf7b,
0xbdc9bf6d,0x3f7fbec4,0x3f463ec4,0xbf223f6d,0xbef13f7b,0xbf62be48,0xbe95bf55,0x3f75bf0e,0xbec43f80,0xbf6d8000,0x3ec4bf80,0x3f6d8000,
0x3f6dbf35,0x3ec43f35,0xbf6d3f35,0xbec4bf35,0xbf6d0000,0x3ec4bf80,0x3f6d0000,0xbec43f80,0x3ec43f35,0xbf6d3f35,0xbec4bf35,0x3f6dbf35,
0x3f620000,0xbef13f80,0xbe95bf35,0x3f75bf35,0xbdc9bf55,0x3f7fbf0e,0xbf223f7b,0xbf46be48,0xbf463f6d,0xbf22bec4,0x3f7fbec4,0xbdc93f6d,
0x3f75be48,0xbe953f7b,0xbef1bf0e,0x3f62bf55,0x3f0ebf80,0x3f558000,0xbf550000,0x3f0ebf80,0xbf7b3ec4,0x3e48bf6d,0xbe483f6d,0xbf7b3ec4,
0x3e483f35,0xbf7b3f35,0x3f7bbf35,0x3e483f35,0x3f55bf6d,0x3f0e3ec4,0xbf0ebec4,0x3f55bf6d,0xbf460000,0x3f22bf80,0xbf7f3f35,0xbdc9bf35,
0xbef13f7b,0xbf623e48,0x3e953f0e,0xbf753f55,0x3f75bec4,0xbe953f6d,0x3f62bf6d,0x3ef13ec4,0x3dc9bf55,0x3f7fbf0e,0xbf22be48,0x3f46bf7b,
0xbf353f80,0xbf358000,0xbf353f80,0xbf358000,0x3f350000,0xbf353f80,0x3f350000,0xbf353f80,0x3f35bf80,0x3f358000,0x3f35bf80,0x3f358000,
0xbf350000,0x3f35bf80,0xbf350000,0x3f35bf80,0x3f220000,0xbf463f80,0xbdc93f35,0xbf7f3f35,0x3f62bf7b,0x3ef13e48,0x3f75bf0e,0xbe953f55,
0xbe95bec4,0x3f75bf6d,0x3ef1bf6d,0x3f62bec4,0xbf7f3f55,0xbdc9bf0e,0xbf463e48,0x3f22bf7b,0x3f55bf80,0x3f0e8000,0x3f0e0000,0xbf553f80,
0xbe48bec4,0x3f7bbf6d,0x3f7bbf6d,0x3e483ec4,0xbf7b3f35,0x3e48bf35,0x3e48bf35,0x3f7bbf35,0xbf0e3f6d,0xbf553ec4,0xbf553ec4,0x3f0ebf6d,
0xbef10000,0x3f62bf80,0x3f75bf35,0xbe953f35,0xbf7f3f55,0x3dc9bf0e,0x3f46bf7b,0x3f22be48,0xbf223f6d,0xbf463ec4,0xbdc9bec4,0x3f7fbf6d,
0x3e953e48,0xbf753f7b,0xbf623f0e,0x3ef1bf55,0xbf6d3f80,0xbec48000,0x3f6dbf80,0x3ec48000,0xbec43f35,0xbf6d3f35,0x3ec4bf35,0x3f6dbf35,
0x3ec40000,0xbf6d3f80,0xbec40000,0x3f6dbf80,0x3f6dbf35,0xbec43f35,0xbf6d3f35,0x3ec4bf35,0x3e950000,0xbf753f80,0x3ef1bf35,0x3f62bf35,
0x3f46bf0e,0xbf223f55,0xbdc9be48,0x3f7fbf7b,0x3f7fbf6d,0xbdc93ec4,0xbf223ec4,0x3f46bf6d,0x3f62bf7b,0x3ef1be48,0xbf753f55,0x3e95bf0e,
0x3f7bbf80,0x3e488000,0xbe480000,0x3f7bbf80,0x3f55bf6d,0x3f0ebec4,0xbf0e3ec4,0x3f55bf6d,0x3f0ebf35,0x3f55bf35,0xbf553f35,0x3f0ebf35,
0x3e48bec4,0x3f7bbf6d,0xbf7b3f6d,0x3e48bec4,0xbdc90000,0x3f7fbf80,0xbf463f35,0x3f22bf35,0xbe953e48,0x3f75bf7b,0xbf623f55,0x3ef1bf0e,
0xbef13ec4,0x3f62bf6d,0xbf753f6d,0x3e95bec4,0xbf223f0e,0x3f46bf55,0xbf7f3f7b,0x3dc9be48,0x3f803f80,0xbf353f35,0x3f803f80,0xbf353f35,
0x3f803f80,0xbf353f35,0x3f803f80,0xbf353f35,0x3f803f80,0xbf353f35,0x3f803f80,0xbf353f35,0x3f803f80,0xbf353f35,0x3f803f80,0xbf353f35,
0x3f7e3f80,0xbdfbbcc9,0x3f1d3f31,0xbf4abf39,0x3f733f7a,0xbea1be60,0x3ee63f09,0xbf65bf58,0x3f5f3f6a,0xbefcbecf,0x3e893eb8,0xbf77bf6f,
0x3f423f51,0xbf27bf13,0x3d973e2f,0xbf7fbf7c,0x3f783f80,0xbe79bd49,0xbe79bd49,0xbf78bf80,0x3f4e3f67,0xbf18bedb,0xbf18bedb,0xbf4ebf67,
0x3f043f2c,0xbf5cbf3e,0xbf5cbf3e,0xbf04bf2c,0x3e163eac,0xbf7dbf71,0xbf7dbf71,0xbe16beac,0x3f6f3f7f,0xbeb8bd97,0xbf6abf42,0xbecfbf27,
0x3f133f4a,0xbf51bf1d,0xbf7cbf7e,0x3e2fbdfb,0x3cc93ea1,0xbf80bf73,0xbf39bf65,0x3f313ee6,0xbf09be89,0xbf58bf77,0xbe60befc,0x3f7a3f5f,
0x3f623f7f,0xbef1bdc9,0xbf62bf7f,0x3ef13dc9,0x3e953f22,0xbf75bf46,0xbe95bf22,0x3f753f46,0xbef1bdc9,0xbf62bf7f,0x3ef13dc9,0x3f623f7f,
0xbf75bf46,0xbe95bf22,0x3f753f46,0x3e953f22,0x3f513f7e,0xbf13bdfb,0xbe2fbf1d,0x3f7c3f4a,0xbcc93ee6,0xbf80bf65,0x3f393ea1,0x3f313f73,
0xbf58befc,0xbf09bf5f,0x3f7a3f77,0xbe603e89,0xbf6abf7f,0x3ecfbd97,0x3eb83f42,0xbf6fbf27,0x3f3e3f7d,0xbf2cbe16,0x3f2c3e16,0x3f3e3f7d,
0xbeac3e79,0xbf71bf78,0x3f713f78,0xbeac3e79,0xbf80bf4e,0xbd49bf18,0x3d493f18,0xbf80bf4e,0xbedbbf5c,0x3f673f04,0xbf67bf04,0xbedbbf5c,
0x3f273f7c,0xbf42be2f,0x3f7f3f51,0xbd973f13,0xbf1d3cc9,0xbf4abf80,0x3dfb3f39,0xbf7ebf31,0xbf65bf7a,0x3ee6be60,0xbf73bf09,0xbea1bf58,
0x3e89becf,0x3f773f6a,0xbefcbf6f,0x3f5f3eb8,0x3f0e3f7b,0xbf55be48,0x3f0e3f7b,0xbf55be48,0xbf55be48,0xbf0ebf7b,0xbf55be48,0xbf0ebf7b,
0xbf0ebf7b,0x3f553e48,0xbf0ebf7b,0x3f553e48,0x3f553e48,0x3f0e3f7b,0x3f553e48,0x3f0e3f7b,0x3ee63f7a,0xbf65be60,0xbea13f09,0xbf73bf58,
0xbf77becf,0xbe89bf6a,0xbf5fbf6f,0x3efcbeb8,0xbd97bf51,0x3f7f3f13,0x3f27be2f,0x3f423f7c,0x3f7e3f39,0xbdfb3f31,0x3f1d3f80,0xbf4abcc9,
0x3eac3f78,0xbf71be79,0xbf71be79,0xbeacbf78,0xbf80bf18,0x3d49bf4e,0x3d49bf4e,0x3f803f18,0x3edbbf04,0x3f673f5c,0x3f673f5c,0xbedb3f04,
0x3f2c3f7d,0xbf3e3e16,0xbf3e3e16,0xbf2cbf7d,0x3e603f77,0xbf7abe89,0xbf58bf5f,0x3f09befc,0xbf6fbf42,0x3eb8bf27,0x3f6a3d97,0x3ecf3f7f,
0x3f51bdfb,0x3f133f7e,0xbe2f3f4a,0xbf7cbf1d,0x3cc93f65,0xbf80bee6,0xbf39bf73,0x3f31bea1,0x3dc93f75,0xbf7fbe95,0xbdc9bf75,0x3f7f3e95,
0xbf46bf62,0x3f22bef1,0x3f463f62,0xbf223ef1,0x3f7f3e95,0x3dc93f75,0xbf7fbe95,0xbdc9bf75,0xbf223ef1,0xbf46bf62,0x3f22bef1,0x3f463f62,
0xbcc93f73,0xbf80bea1,0x3f39bee6,0x3f313f65,0xbf09bf77,0x3f58be89,0xbe603f5f,0xbf7abefc,0x3f6a3f27,0xbecf3f42,0xbeb8bf7f,0x3f6fbd97,
0xbf7cbdfb,0xbe2fbf7e,0x3f513f4a,0xbf133f1d,0xbe163f71,0xbf7dbeac,0x3f7d3eac,0xbe163f71,0xbe79bf80,0x3f78bd49,0xbf783d49,0xbe79bf80,
0x3f183f67,0xbf4e3edb,0x3f4ebedb,0x3f183f67,0xbf5cbf2c,0x3f04bf3e,0xbf043f3e,0xbf5cbf2c,0xbe893f6f,0xbf77beb8,0x3efc3f6a,0xbf5f3ecf,
0x3d97bf7c,0x3f7f3e2f,0xbf27bf51,0x3f42bf13,0x3dfb3f80,0xbf7e3cc9,0x3f4a3f31,0xbf1d3f39,0xbea1bf7a,0x3f73be60,0xbf65bf09,0x3ee6bf58,
0xbec43f6d,0xbf6dbec4,0xbec43f6d,0xbf6dbec4,0x3ec4bf6d,0x3f6d3ec4,0x3ec4bf6d,0x3f6d3ec4,0xbec43f6d,0xbf6dbec4,0xbec43f6d,0xbf6dbec4,
0x3ec4bf6d,0x3f6d3ec4,0x3ec4bf6d,0x3f6d3ec4,0xbefc3f6a,0xbf5fbecf,0xbf773eb8,0xbe89bf6f,0x3f27bf51,0x3f423f13,0x3f7fbe2f,0x3d973f7c,
0xbf4a3f31,0xbf1dbf39,0xbf7ebcc9,0x3dfbbf80,0x3f65bf09,0x3ee63f58,0x3f733e60,0xbea13f7a,0xbf183f67,0xbf4ebedb,0xbf4ebedb,0x3f18bf67,
0x3f5cbf2c,0x3f043f3e,0x3f043f3e,0xbf5c3f2c,0xbf7d3eac,0xbe16bf71,0xbe16bf71,0x3f7dbeac,0x3f783d49,0xbe793f80,0xbe793f80,0xbf78bd49,
0xbf313f65,0xbf39bee6,0xbcc9bf73,0x3f80bea1,0x3f7abefc,0x3e603f5f,0xbf093f77,0xbf58be89,0xbf6fbd97,0x3eb8bf7f,0x3f6abf27,0x3ecf3f42,
0x3f133f1d,0xbf513f4a,0xbf7c3dfb,0x3e2fbf7e,0xbf463f62,0xbf22bef1,0x3f46bf62,0x3f223ef1,0x3f7fbe95,0xbdc93f75,0xbf7f3e95,0x3dc9bf75,
0xbf22bef1,0x3f46bf62,0x3f223ef1,0xbf463f62,0xbdc93f75,0xbf7f3e95,0x3dc9bf75,0x3f7fbe95,0xbf583f5f,0xbf09befc,0x3f7abe89,0xbe603f77,
0x3f6abd97,0xbecf3f7f,0xbeb8bf27,0x3f6fbf42,0xbe2fbf4a,0x3f7cbf1d,0xbf133f7e,0xbf51bdfb,0xbf393f73,0xbf31bea1,0x3f80bee6,0xbcc93f65,
0xbf673f5c,0xbedbbf04,0x3edb3f04,0xbf673f5c,0x3f3e3e16,0xbf2c3f7d,0x3f2cbf7d,0x3f3e3e16,0x3eacbf78,0x3f71be79,0xbf713e79,0x3eacbf78,
0xbf803f18,0xbd49bf4e,0x3d493f4e,0xbf803f18,0xbf733f58,0xbea1bf09,0xbee63f7a,0xbf653e60,0x3efc3eb8,0xbf5f3f6f,0x3f77becf,0xbe893f6a,
0x3f42bf7c,0x3f273e2f,0x3d97bf51,0x3f7fbf13,0xbf4a3cc9,0x3f1dbf80,0xbf7e3f39,0xbdfbbf31,0xbf7b3f55,0xbe48bf0e,0xbf7b3f55,0xbe48bf0e,
0x3e483f0e,0xbf7b3f55,0x3e483f0e,0xbf7b3f55,0x3f7bbf55,0x3e483f0e,0x3f7bbf55,0x3e483f0e,0xbe48bf0e,0x3f7bbf55,0xbe48bf0e,0x3f7bbf55,
0xbf7f3f51,0xbd97bf13,0xbf423e2f,0x3f27bf7c,0xbdfb3f39,0xbf7e3f31,0xbf4a3f80,0xbf1dbcc9,0x3f73bf09,0xbea13f58,0x3ee63e60,0xbf653f7a,
0x3efcbf6f,0x3f5fbeb8,0x3f77bf6a,0x3e893ecf,0xbf803f4e,0x3d49bf18,0x3d49bf18,0x3f80bf4e,0xbedb3f5c,0xbf673f04,0xbf673f04,0x3edbbf5c,
0x3f2cbe16,0xbf3e3f7d,0xbf3e3f7d,0xbf2c3e16,0x3f71bf78,0x3eac3e79,0x3eac3e79,0xbf713f78,0xbf7c3f4a,0x3e2fbf1d,0x3f51bf7e,0x3f13bdfb,
0xbf313f73,0xbf393ea1,0xbcc9bee6,0x3f80bf65,0x3e603e89,0xbf7a3f77,0xbf583efc,0x3f09bf5f,0x3f6fbf27,0xbeb83f42,0xbf6a3f7f,0xbecfbd97,
0xbf753f46,0x3e95bf22,0x3f75bf46,0xbe953f22,0xbf623f7f,0xbef13dc9,0x3f62bf7f,0x3ef1bdc9,0xbe953f22,0xbf753f46,0x3e95bf22,0x3f75bf46,
0x3ef1bdc9,0xbf623f7f,0xbef13dc9,0x3f62bf7f,0xbf6a3f42,0x3ecfbf27,0x3eb8bd97,0xbf6f3f7f,0xbf7c3f7e,0xbe2fbdfb,0x3f51bf1d,0xbf133f4a,
0xbf393f65,0xbf313ee6,0x3f80bf73,0xbcc93ea1,0xbe603efc,0xbf7a3f5f,0x3f58bf77,0x3f09be89,0xbf5c3f3e,0x3f04bf2c,0xbf043f2c,0xbf5c3f3e,
0xbf7d3f71,0x3e16beac,0xbe163eac,0xbf7d3f71,0xbf783f80,0xbe793d49,0x3e79bd49,0xbf783f80,0xbf4e3f67,0xbf183edb,0x3f18bedb,0xbf4e3f67,
0xbf4a3f39,0x3f1dbf31,0xbf7e3f80,0xbdfb3cc9,0xbf653f58,0x3ee6bf09,0xbf733f7a,0xbea13e60,0xbf773f6f,0x3e89beb8,0xbf5f3f6a,0xbefc3ecf,
0xbf7f3f7c,0x3d97be2f,0xbf423f51,0xbf273f13,0x3f803f80,0xbf353f35,0x3f803f80,0xbf353f35,0x3f803f80,0xbf353f35,0x3f803f80,0xbf353f35,
0x3f803f80,0xbf353f35,0x3f803f80,0xbf353f35,0x3f803f80,0xbf353f35,0x3f803f80,0xbf353f35,0xbdfbbcc9,0xbf7ebf80,0xbf4abf39,0xbf1dbf31,
0xbea1be60,0xbf73bf7a,0xbf65bf58,0xbee6bf09,0xbefcbecf,0xbf5fbf6a,0xbf77bf6f,0xbe89beb8,0xbf27bf13,0xbf42bf51,0xbf7fbf7c,0xbd97be2f,
0xbf78bf80,0x3e793d49,0x3e793d49,0x3f783f80,0xbf4ebf67,0x3f183edb,0x3f183edb,0x3f4e3f67,0xbf04bf2c,0x3f5c3f3e,0x3f5c3f3e,0x3f043f2c,
0xbe16beac,0x3f7d3f71,0x3f7d3f71,0x3e163eac,0x3eb83d97,0x3f6f3f7f,0x3ecf3f27,0xbf6abf42,0x3f513f1d,0x3f133f4a,0xbe2f3dfb,0xbf7cbf7e,
0x3f803f73,0x3cc93ea1,0xbf31bee6,0xbf39bf65,0x3f583f77,0xbf09be89,0xbf7abf5f,0xbe60befc,0x3f623f7f,0xbef1bdc9,0xbf62bf7f,0x3ef13dc9,
0x3e953f22,0xbf75bf46,0xbe95bf22,0x3f753f46,0xbef1bdc9,0xbf62bf7f,0x3ef13dc9,0x3f623f7f,0xbf75bf46,0xbe95bf22,0x3f753f46,0x3e953f22,
0xbf13bdfb,0xbf51bf7e,0x3f7c3f4a,0x3e2f3f1d,0xbf80bf65,0x3cc9bee6,0x3f313f73,0xbf39bea1,0xbf09bf5f,0x3f583efc,0xbe603e89,0xbf7abf77,
0x3ecfbd97,0x3f6a3f7f,0xbf6fbf27,0xbeb8bf42,0xbf3ebf7d,0x3f2c3e16,0xbf2cbe16,0xbf3ebf7d,0x3eacbe79,0x3f713f78,0xbf71bf78,0x3eacbe79,
0x3f803f4e,0x3d493f18,0xbd49bf18,0x3f803f4e,0x3edb3f5c,0xbf67bf04,0x3f673f04,0x3edb3f5c,0x3f423e2f,0x3f273f7c,0x3d97bf13,0x3f7f3f51,
0x3f4a3f80,0xbf1d3cc9,0x3f7e3f31,0x3dfb3f39,0xbee63e60,0xbf65bf7a,0x3ea13f58,0xbf73bf09,0xbf77bf6a,0x3e89becf,0xbf5fbeb8,0xbefcbf6f,
0x3f0e3f7b,0xbf55be48,0x3f0e3f7b,0xbf55be48,0xbf55be48,0xbf0ebf7b,0xbf55be48,0xbf0ebf7b,0xbf0ebf7b,0x3f553e48,0xbf0ebf7b,0x3f553e48,
0x3f553e48,0x3f0e3f7b,0x3f553e48,0x3f0e3f7b,0xbf65be60,0xbee6bf7a,0xbf73bf58,0x3ea1bf09,0xbe89bf6a,0x3f773ecf,0x3efcbeb8,0x3f5f3f6f,
0x3f7f3f13,0x3d973f51,0x3f423f7c,0xbf273e2f,0xbdfb3f31,0xbf7ebf39,0xbf4abcc9,0xbf1dbf80,0xbeacbf78,0x3f713e79,0x3f713e79,0x3eac3f78,
0x3f803f18,0xbd493f4e,0xbd493f4e,0xbf80bf18,0xbedb3f04,0xbf67bf5c,0xbf67bf5c,0x3edbbf04,0xbf2cbf7d,0x3f3ebe16,0x3f3ebe16,0x3f2c3f7d,
0x3f7a3e89,0x3e603f77,0xbf093efc,0xbf58bf5f,0xbeb83f27,0xbf6fbf42,0xbecfbf7f,0x3f6a3d97,0xbf13bf7e,0x3f51bdfb,0x3f7c3f1d,0xbe2f3f4a,
0x3f803ee6,0x3cc93f65,0xbf313ea1,0xbf39bf73,0x3dc93f75,0xbf7fbe95,0xbdc9bf75,0x3f7f3e95,0xbf46bf62,0x3f22bef1,0x3f463f62,0xbf223ef1,
0x3f7f3e95,0x3dc93f75,0xbf7fbe95,0xbdc9bf75,0xbf223ef1,0xbf46bf62,0x3f22bef1,0x3f463f62,0xbf80bea1,0x3cc9bf73,0x3f313f65,0xbf393ee6,
0x3f58be89,0x3f093f77,0xbf7abefc,0x3e60bf5f,0xbecf3f42,0xbf6abf27,0x3f6fbd97,0x3eb83f7f,0xbe2fbf7e,0x3f7c3dfb,0xbf133f1d,0xbf51bf4a,
0x3e16bf71,0x3f7d3eac,0xbf7dbeac,0x3e16bf71,0x3e793f80,0xbf783d49,0x3f78bd49,0x3e793f80,0xbf18bf67,0x3f4ebedb,0xbf4e3edb,0xbf18bf67,
0x3f5c3f2c,0xbf043f3e,0x3f04bf3e,0x3f5c3f2c,0x3f773eb8,0xbe893f6f,0x3f5fbecf,0x3efc3f6a,0xbf7fbe2f,0x3d97bf7c,0xbf423f13,0xbf27bf51,
0x3f7ebcc9,0x3dfb3f80,0x3f1dbf39,0x3f4a3f31,0xbf733e60,0xbea1bf7a,0xbee63f58,0xbf65bf09,0xbec43f6d,0xbf6dbec4,0xbec43f6d,0xbf6dbec4,
0x3ec4bf6d,0x3f6d3ec4,0x3ec4bf6d,0x3f6d3ec4,0xbec43f6d,0xbf6dbec4,0xbec43f6d,0xbf6dbec4,0x3ec4bf6d,0x3f6d3ec4,0x3ec4bf6d,0x3f6d3ec4,
0xbf5fbecf,0x3efcbf6a,0xbe89bf6f,0x3f77beb8,0x3f423f13,0xbf273f51,0x3d973f7c,0xbf7f3e2f,0xbf1dbf39,0x3f4abf31,0x3dfbbf80,0x3f7e3cc9,
0x3ee63f58,0xbf653f09,0xbea13f7a,0xbf73be60,0x3f18bf67,0x3f4e3edb,0x3f4e3edb,0xbf183f67,0xbf5c3f2c,0xbf04bf3e,0xbf04bf3e,0x3f5cbf2c,
0x3f7dbeac,0x3e163f71,0x3e163f71,0xbf7d3eac,0xbf78bd49,0x3e79bf80,0x3e79bf80,0x3f783d49,0x3f393ee6,0xbf313f65,0xbf803ea1,0xbcc9bf73,
0xbe60bf5f,0x3f7abefc,0x3f583e89,0xbf093f77,0xbeb83f7f,0xbf6fbd97,0xbecfbf42,0x3f6abf27,0x3f51bf4a,0x3f133f1d,0xbe2f3f7e,0xbf7c3dfb,
0xbf463f62,0xbf22bef1,0x3f46bf62,0x3f223ef1,0x3f7fbe95,0xbdc93f75,0xbf7f3e95,0x3dc9bf75,0xbf22bef1,0x3f46bf62,0x3f223ef1,0xbf463f62,
0xbdc93f75,0xbf7f3e95,0x3dc9bf75,0x3f7fbe95,0xbf09befc,0x3f58bf5f,0xbe603f77,0xbf7a3e89,0xbecf3f7f,0xbf6a3d97,0x3f6fbf42,0x3eb83f27,
0x3f7cbf1d,0x3e2f3f4a,0xbf51bdfb,0x3f13bf7e,0xbf31bea1,0x3f39bf73,0xbcc93f65,0xbf803ee6,0x3f67bf5c,0x3edb3f04,0xbedbbf04,0x3f67bf5c,
0xbf3ebe16,0x3f2cbf7d,0xbf2c3f7d,0xbf3ebe16,0xbeac3f78,0xbf713e79,0x3f71be79,0xbeac3f78,0x3f80bf18,0x3d493f4e,0xbd49bf4e,0x3f80bf18,
0x3ea13f09,0xbf733f58,0x3f65be60,0xbee63f7a,0x3f5fbf6f,0x3efc3eb8,0x3e89bf6a,0x3f77becf,0xbf27be2f,0x3f42bf7c,0xbf7f3f13,0x3d97bf51,
0xbf1d3f80,0xbf4a3cc9,0x3dfb3f31,0xbf7e3f39,0xbf7b3f55,0xbe48bf0e,0xbf7b3f55,0xbe48bf0e,0x3e483f0e,0xbf7b3f55,0x3e483f0e,0xbf7b3f55,
0x3f7bbf55,0x3e483f0e,0x3f7bbf55,0x3e483f0e,0xbe48bf0e,0x3f7bbf55,0xbe48bf0e,0x3f7bbf55,0xbd97bf13,0x3f7fbf51,0x3f27bf7c,0x3f42be2f,
0xbf7e3f31,0x3dfbbf39,0xbf1dbcc9,0x3f4abf80,0xbea13f58,0xbf733f09,0xbf653f7a,0xbee6be60,0x3f5fbeb8,0xbefc3f6f,0x3e893ecf,0xbf773f6a,
0x3f80bf4e,0xbd493f18,0xbd493f18,0xbf803f4e,0x3edbbf5c,0x3f67bf04,0x3f67bf04,0xbedb3f5c,0xbf2c3e16,0x3f3ebf7d,0x3f3ebf7d,0x3f2cbe16,
0xbf713f78,0xbeacbe79,0xbeacbe79,0x3f71bf78,0xbe2f3f1d,0xbf7c3f4a,0xbf133dfb,0x3f51bf7e,0x3f39bea1,0xbf313f73,0xbf803f65,0xbcc9bee6,
0x3f7abf77,0x3e603e89,0xbf093f5f,0xbf583efc,0x3eb8bf42,0x3f6fbf27,0x3ecf3d97,0xbf6a3f7f,0xbf753f46,0x3e95bf22,0x3f75bf46,0xbe953f22,
0xbf623f7f,0xbef13dc9,0x3f62bf7f,0x3ef1bdc9,0xbe953f22,0xbf753f46,0x3e95bf22,0x3f75bf46,0x3ef1bdc9,0xbf623f7f,0xbef13dc9,0x3f62bf7f,
0x3ecfbf27,0x3f6abf42,0xbf6f3f7f,0xbeb83d97,0xbe2fbdfb,0x3f7cbf7e,0xbf133f4a,0xbf513f1d,0xbf313ee6,0x3f39bf65,0xbcc93ea1,0xbf803f73,
0xbf7a3f5f,0x3e60befc,0x3f09be89,0xbf583f77,0x3f5cbf3e,0xbf043f2c,0x3f04bf2c,0x3f5cbf3e,0x3f7dbf71,0xbe163eac,0x3e16beac,0x3f7dbf71,
0x3f78bf80,0x3e79bd49,0xbe793d49,0x3f78bf80,0x3f4ebf67,0x3f18bedb,0xbf183edb,0x3f4ebf67,0xbf1d3f31,0xbf4a3f39,0x3dfbbcc9,0xbf7e3f80,
0xbee63f09,0xbf653f58,0x3ea1be60,0xbf733f7a,0xbe893eb8,0xbf773f6f,0x3efcbecf,0xbf5f3f6a,0xbd973e2f,0xbf7f3f7c,0x3f27bf13,0xbf423f51,
0x3f803f80,0xbf353f35,0x3f803f80,0xbf353f35,0x3f803f80,0xbf353f35,0x3f803f80,0xbf353f35,0x3f803f80,0xbf353f35,0x3f803f80,0xbf353f35,
0x3f803f80,0xbf353f35,0x3f803f80,0xbf353f35,0xbf7ebf80,0x3dfb3cc9,0xbf1dbf31,0x3f4a3f39,0xbf73bf7a,0x3ea13e60,0xbee6bf09,0x3f653f58,
0xbf5fbf6a,0x3efc3ecf,0xbe89beb8,0x3f773f6f,0xbf42bf51,0x3f273f13,0xbd97be2f,0x3f7f3f7c,0x3f783f80,0xbe79bd49,0xbe79bd49,0xbf78bf80,
0x3f4e3f67,0xbf18bedb,0xbf18bedb,0xbf4ebf67,0x3f043f2c,0xbf5cbf3e,0xbf5cbf3e,0xbf04bf2c,0x3e163eac,0xbf7dbf71,0xbf7dbf71,0xbe16beac,
0xbf6fbf7f,0x3eb83d97,0x3f6a3f42,0x3ecf3f27,0xbf13bf4a,0x3f513f1d,0x3f7c3f7e,0xbe2f3dfb,0xbcc9bea1,0x3f803f73,0x3f393f65,0xbf31bee6,
0x3f093e89,0x3f583f77,0x3e603efc,0xbf7abf5f,0x3f623f7f,0xbef1bdc9,0xbf62bf7f,0x3ef13dc9,0x3e953f22,0xbf75bf46,0xbe95bf22,0x3f753f46,
0xbef1bdc9,0xbf62bf7f,0x3ef13dc9,0x3f623f7f,0xbf75bf46,0xbe95bf22,0x3f753f46,0x3e953f22,0xbf51bf7e,0x3f133dfb,0x3e2f3f1d,0xbf7cbf4a,
0x3cc9bee6,0x3f803f65,0xbf39bea1,0xbf31bf73,0x3f583efc,0x3f093f5f,0xbf7abf77,0x3e60be89,0x3f6a3f7f,0xbecf3d97,0xbeb8bf42,0x3f6f3f27,
0x3f3e3f7d,0xbf2cbe16,0x3f2c3e16,0x3f3e3f7d,0xbeac3e79,0xbf71bf78,0x3f713f78,0xbeac3e79,0xbf80bf4e,0xbd49bf18,0x3d493f18,0xbf80bf4e,
0xbedbbf5c,0x3f673f04,0xbf67bf04,0xbedbbf5c,0xbf27bf7c,0x3f423e2f,0xbf7fbf51,0x3d97bf13,0x3f1dbcc9,0x3f4a3f80,0xbdfbbf39,0x3f7e3f31,
0x3f653f7a,0xbee63e60,0x3f733f09,0x3ea13f58,0xbe893ecf,0xbf77bf6a,0x3efc3f6f,0xbf5fbeb8,0x3f0e3f7b,0xbf55be48,0x3f0e3f7b,0xbf55be48,
0xbf55be48,0xbf0ebf7b,0xbf55be48,0xbf0ebf7b,0xbf0ebf7b,0x3f553e48,0xbf0ebf7b,0x3f553e48,0x3f553e48,0x3f0e3f7b,0x3f553e48,0x3f0e3f7b,
0xbee6bf7a,0x3f653e60,0x3ea1bf09,0x3f733f58,0x3f773ecf,0x3e893f6a,0x3f5f3f6f,0xbefc3eb8,0x3d973f51,0xbf7fbf13,0xbf273e2f,0xbf42bf7c,
0xbf7ebf39,0x3dfbbf31,0xbf1dbf80,0x3f4a3cc9,0x3eac3f78,0xbf71be79,0xbf71be79,0xbeacbf78,0xbf80bf18,0x3d49bf4e,0x3d49bf4e,0x3f803f18,
0x3edbbf04,0x3f673f5c,0x3f673f5c,0xbedb3f04,0x3f2c3f7d,0xbf3e3e16,0xbf3e3e16,0xbf2cbf7d,0xbe60bf77,0x3f7a3e89,0x3f583f5f,0xbf093efc,
0x3f6f3f42,0xbeb83f27,0xbf6abd97,0xbecfbf7f,0xbf513dfb,0xbf13bf7e,0x3e2fbf4a,0x3f7c3f1d,0xbcc9bf65,0x3f803ee6,0x3f393f73,0xbf313ea1,
0x3dc93f75,0xbf7fbe95,0xbdc9bf75,0x3f7f3e95,0xbf46bf62,0x3f22bef1,0x3f463f62,0xbf223ef1,0x3f7f3e95,0x3dc93f75,0xbf7fbe95,0xbdc9bf75,
0xbf223ef1,0xbf46bf62,0x3f22bef1,0x3f463f62,0x3cc9bf73,0x3f803ea1,0xbf393ee6,0xbf31bf65,0x3f093f77,0xbf583e89,0x3e60bf5f,0x3f7a3efc,
0xbf6abf27,0x3ecfbf42,0x3eb83f7f,0xbf6f3d97,0x3f7c3dfb,0x3e2f3f7e,0xbf51bf4a,0x3f13bf1d,0xbe163f71,0xbf7dbeac,0x3f7d3eac,0xbe163f71,
0xbe79bf80,0x3f78bd49,0xbf783d49,0xbe79bf80,0x3f183f67,0xbf4e3edb,0x3f4ebedb,0x3f183f67,0xbf5cbf2c,0x3f04bf3e,0xbf043f3e,0xbf5cbf2c,
0x3e89bf6f,0x3f773eb8,0xbefcbf6a,0x3f5fbecf,0xbd973f7c,0xbf7fbe2f,0x3f273f51,0xbf423f13,0xbdfbbf80,0x3f7ebcc9,0xbf4abf31,0x3f1dbf39,
0x3ea13f7a,0xbf733e60,0x3f653f09,0xbee63f58,0xbec43f6d,0xbf6dbec4,0xbec43f6d,0xbf6dbec4,0x3ec4bf6d,0x3f6d3ec4,0x3ec4bf6d,0x3f6d3ec4,
0xbec43f6d,0xbf6dbec4,0xbec43f6d,0xbf6dbec4,0x3ec4bf6d,0x3f6d3ec4,0x3ec4bf6d,0x3f6d3ec4,0x3efcbf6a,0x3f5f3ecf,0x3f77beb8,0x3e893f6f,
0xbf273f51,0xbf42bf13,0xbf7f3e2f,0xbd97bf7c,0x3f4abf31,0x3f1d3f39,0x3f7e3cc9,0xbdfb3f80,0xbf653f09,0xbee6bf58,0xbf73be60,0x3ea1bf7a,
0xbf183f67,0xbf4ebedb,0xbf4ebedb,0x3f18bf67,0x3f5cbf2c,0x3f043f3e,0x3f043f3e,0xbf5c3f2c,0xbf7d3eac,0xbe16bf71,0xbe16bf71,0x3f7dbeac,
0x3f783d49,0xbe793f80,0xbe793f80,0xbf78bd49,0x3f31bf65,0x3f393ee6,0x3cc93f73,0xbf803ea1,0xbf7a3efc,0xbe60bf5f,0x3f09bf77,0x3f583e89,
0x3f6f3d97,0xbeb83f7f,0xbf6a3f27,0xbecfbf42,0xbf13bf1d,0x3f51bf4a,0x3f7cbdfb,0xbe2f3f7e,0xbf463f62,0xbf22bef1,0x3f46bf62,0x3f223ef1,
0x3f7fbe95,0xbdc93f75,0xbf7f3e95,0x3dc9bf75,0xbf22bef1,0x3f46bf62,0x3f223ef1,0xbf463f62,0xbdc93f75,0xbf7f3e95,0x3dc9bf75,0x3f7fbe95,
0x3f58bf5f,0x3f093efc,0xbf7a3e89,0x3e60bf77,0xbf6a3d97,0x3ecfbf7f,0x3eb83f27,0xbf6f3f42,0x3e2f3f4a,0xbf7c3f1d,0x3f13bf7e,0x3f513dfb,
0x3f39bf73,0x3f313ea1,0xbf803ee6,0x3cc9bf65,0xbf673f5c,0xbedbbf04,0x3edb3f04,0xbf673f5c,0x3f3e3e16,0xbf2c3f7d,0x3f2cbf7d,0x3f3e3e16,
0x3eacbf78,0x3f71be79,0xbf713e79,0x3eacbf78,0xbf803f18,0xbd49bf4e,0x3d493f4e,0xbf803f18,0x3f73bf58,0x3ea13f09,0x3ee6bf7a,0x3f65be60,
0xbefcbeb8,0x3f5fbf6f,0xbf773ecf,0x3e89bf6a,0xbf423f7c,0xbf27be2f,0xbd973f51,0xbf7f3f13,0x3f4abcc9,0xbf1d3f80,0x3f7ebf39,0x3dfb3f31,
0xbf7b3f55,0xbe48bf0e,0xbf7b3f55,0xbe48bf0e,0x3e483f0e,0xbf7b3f55,0x3e483f0e,0xbf7b3f55,0x3f7bbf55,0x3e483f0e,0x3f7bbf55,0x3e483f0e,
0xbe48bf0e,0x3f7bbf55,0xbe48bf0e,0x3f7bbf55,0x3f7fbf51,0x3d973f13,0x3f42be2f,0xbf273f7c,0x3dfbbf39,0x3f7ebf31,0x3f4abf80,0x3f1d3cc9,
0xbf733f09,0x3ea1bf58,0xbee6be60,0x3f65bf7a,0xbefc3f6f,0xbf5f3eb8,0xbf773f6a,0xbe89becf,0xbf803f4e,0x3d49bf18,0x3d49bf18,0x3f80bf4e,
0xbedb3f5c,0xbf673f04,0xbf673f04,0x3edbbf5c,0x3f2cbe16,0xbf3e3f7d,0xbf3e3f7d,0xbf2c3e16,0x3f71bf78,0x3eac3e79,0x3eac3e79,0xbf713f78,
0x3f7cbf4a,0xbe2f3f1d,0xbf513f7e,0xbf133dfb,0x3f31bf73,0x3f39bea1,0x3cc93ee6,0xbf803f65,0xbe60be89,0x3f7abf77,0x3f58befc,0xbf093f5f,
0xbf6f3f27,0x3eb8bf42,0x3f6abf7f,0x3ecf3d97,0xbf753f46,0x3e95bf22,0x3f75bf46,0xbe953f22,0xbf623f7f,0xbef13dc9,0x3f62bf7f,0x3ef1bdc9,
0xbe953f22,0xbf753f46,0x3e95bf22,0x3f75bf46,0x3ef1bdc9,0xbf623f7f,0xbef13dc9,0x3f62bf7f,0x3f6abf42,0xbecf3f27,0xbeb83d97,0x3f6fbf7f,
0x3f7cbf7e,0x3e2f3dfb,0xbf513f1d,0x3f13bf4a,0x3f39bf65,0x3f31bee6,0xbf803f73,0x3cc9bea1,0x3e60befc,0x3f7abf5f,0xbf583f77,0xbf093e89,
0xbf5c3f3e,0x3f04bf2c,0xbf043f2c,0xbf5c3f3e,0xbf7d3f71,0x3e16beac,0xbe163eac,0xbf7d3f71,0xbf783f80,0xbe793d49,0x3e79bd49,0xbf783f80,
0xbf4e3f67,0xbf183edb,0x3f18bedb,0xbf4e3f67,0x3f4abf39,0xbf1d3f31,0x3f7ebf80,0x3dfbbcc9,0x3f65bf58,0xbee63f09,0x3f73bf7a,0x3ea1be60,
0x3f77bf6f,0xbe893eb8,0x3f5fbf6a,0x3efcbecf,0x3f7fbf7c,0xbd973e2f,0x3f42bf51,0x3f27bf13,0x3f803f80,0xbf353f35,0x3f803f80,0xbf353f35,
0x3f803f80,0xbf353f35,0x3f803f80,0xbf353f35,0x3f803f80,0xbf353f35,0x3f803f80,0xbf353f35,0x3f803f80,0xbf353f35,0x3f803f80,0xbf353f35,
0x3dfb3cc9,0x3f7e3f80,0x3f4a3f39,0x3f1d3f31,0x3ea13e60,0x3f733f7a,0x3f653f58,0x3ee63f09,0x3efc3ecf,0x3f5f3f6a,0x3f773f6f,0x3e893eb8,
0x3f273f13,0x3f423f51,0x3f7f3f7c,0x3d973e2f,0xbf78bf80,0x3e793d49,0x3e793d49,0x3f783f80,0xbf4ebf67,0x3f183edb,0x3f183edb,0x3f4e3f67,
0xbf04bf2c,0x3f5c3f3e,0x3f5c3f3e,0x3f043f2c,0xbe16beac,0x3f7d3f71,0x3f7d3f71,0x3e163eac,0xbeb8bd97,0xbf6fbf7f,0xbecfbf27,0x3f6a3f42,
0xbf51bf1d,0xbf13bf4a,0x3e2fbdfb,0x3f7c3f7e,0xbf80bf73,0xbcc9bea1,0x3f313ee6,0x3f393f65,0xbf58bf77,0x3f093e89,0x3f7a3f5f,0x3e603efc,
0x3f623f7f,0xbef1bdc9,0xbf62bf7f,0x3ef13dc9,0x3e953f22,0xbf75bf46,0xbe95bf22,0x3f753f46,0xbef1bdc9,0xbf62bf7f,0x3ef13dc9,0x3f623f7f,
0xbf75bf46,0xbe95bf22,0x3f753f46,0x3e953f22,0x3f133dfb,0x3f513f7e,0xbf7cbf4a,0xbe2fbf1d,0x3f803f65,0xbcc93ee6,0xbf31bf73,0x3f393ea1,
0x3f093f5f,0xbf58befc,0x3e60be89,0x3f7a3f77,0xbecf3d97,0xbf6abf7f,0x3f6f3f27,0x3eb83f42,0xbf3ebf7d,0x3f2c3e16,0xbf2cbe16,0xbf3ebf7d,
0x3eacbe79,0x3f713f78,0xbf71bf78,0x3eacbe79,0x3f803f4e,0x3d493f18,0xbd49bf18,0x3f803f4e,0x3edb3f5c,0xbf67bf04,0x3f673f04,0x3edb3f5c,
0xbf42be2f,0xbf27bf7c,0xbd973f13,0xbf7fbf51,0xbf4abf80,0x3f1dbcc9,0xbf7ebf31,0xbdfbbf39,0x3ee6be60,0x3f653f7a,0xbea1bf58,0x3f733f09,
0x3f773f6a,0xbe893ecf,0x3f5f3eb8,0x3efc3f6f,0x3f0e3f7b,0xbf55be48,0x3f0e3f7b,0xbf55be48,0xbf55be48,0xbf0ebf7b,0xbf55be48,0xbf0ebf7b,
0xbf0ebf7b,0x3f553e48,0xbf0ebf7b,0x3f553e48,0x3f553e48,0x3f0e3f7b,0x3f553e48,0x3f0e3f7b,0x3f653e60,0x3ee63f7a,0x3f733f58,0xbea13f09,
0x3e893f6a,0xbf77becf,0xbefc3eb8,0xbf5fbf6f,0xbf7fbf13,0xbd97bf51,0xbf42bf7c,0x3f27be2f,0x3dfbbf31,0x3f7e3f39,0x3f4a3cc9,0x3f1d3f80,
0xbeacbf78,0x3f713e79,0x3f713e79,0x3eac3f78,0x3f803f18,0xbd493f4e,0xbd493f4e,0xbf80bf18,0xbedb3f04,0xbf67bf5c,0xbf67bf5c,0x3edbbf04,
0xbf2cbf7d,0x3f3ebe16,0x3f3ebe16,0x3f2c3f7d,0xbf7abe89,0xbe60bf77,0x3f09befc,0x3f583f5f,0x3eb8bf27,0x3f6f3f42,0x3ecf3f7f,0xbf6abd97,
0x3f133f7e,0xbf513dfb,0xbf7cbf1d,0x3e2fbf4a,0xbf80bee6,0xbcc9bf65,0x3f31bea1,0x3f393f73,0x3dc93f75,0xbf7fbe95,0xbdc9bf75,0x3f7f3e95,
0xbf46bf62,0x3f22bef1,0x3f463f62,0xbf223ef1,0x3f7f3e95,0x3dc93f75,0xbf7fbe95,0xbdc9bf75,0xbf223ef1,0xbf46bf62,0x3f22bef1,0x3f463f62,
0x3f803ea1,0xbcc93f73,0xbf31bf65,0x3f39bee6,0xbf583e89,0xbf09bf77,0x3f7a3efc,0xbe603f5f,0x3ecfbf42,0x3f6a3f27,0xbf6f3d97,0xbeb8bf7f,
0x3e2f3f7e,0xbf7cbdfb,0x3f13bf1d,0x3f513f4a,0x3e16bf71,0x3f7d3eac,0xbf7dbeac,0x3e16bf71,0x3e793f80,0xbf783d49,0x3f78bd49,0x3e793f80,
0xbf18bf67,0x3f4ebedb,0xbf4e3edb,0xbf18bf67,0x3f5c3f2c,0xbf043f3e,0x3f04bf3e,0x3f5c3f2c,0xbf77beb8,0x3e89bf6f,0xbf5f3ecf,0xbefcbf6a,
0x3f7f3e2f,0xbd973f7c,0x3f42bf13,0x3f273f51,0xbf7e3cc9,0xbdfbbf80,0xbf1d3f39,0xbf4abf31,0x3f73be60,0x3ea13f7a,0x3ee6bf58,0x3f653f09,
0xbec43f6d,0xbf6dbec4,0xbec43f6d,0xbf6dbec4,0x3ec4bf6d,0x3f6d3ec4,0x3ec4bf6d,0x3f6d3ec4,0xbec43f6d,0xbf6dbec4,0xbec43f6d,0xbf6dbec4,
0x3ec4bf6d,0x3f6d3ec4,0x3ec4bf6d,0x3f6d3ec4,0x3f5f3ecf,0xbefc3f6a,0x3e893f6f,0xbf773eb8,0xbf42bf13,0x3f27bf51,0xbd97bf7c,0x3f7fbe2f,
0x3f1d3f39,0xbf4a3f31,0xbdfb3f80,0xbf7ebcc9,0xbee6bf58,0x3f65bf09,0x3ea1bf7a,0x3f733e60,0x3f18bf67,0x3f4e3edb,0x3f4e3edb,0xbf183f67,
0xbf5c3f2c,0xbf04bf3e,0xbf04bf3e,0x3f5cbf2c,0x3f7dbeac,0x3e163f71,0x3e163f71,0xbf7d3eac,0xbf78bd49,0x3e79bf80,0x3e79bf80,0x3f783d49,
0xbf39bee6,0x3f31bf65,0x3f80bea1,0x3cc93f73,0x3e603f5f,0xbf7a3efc,0xbf58be89,0x3f09bf77,0x3eb8bf7f,0x3f6f3d97,0x3ecf3f42,0xbf6a3f27,
0xbf513f4a,0xbf13bf1d,0x3e2fbf7e,0x3f7cbdfb,0xbf463f62,0xbf22bef1,0x3f46bf62,0x3f223ef1,0x3f7fbe95,0xbdc93f75,0xbf7f3e95,0x3dc9bf75,
0xbf22bef1,0x3f46bf62,0x3f223ef1,0xbf463f62,0xbdc93f75,0xbf7f3e95,0x3dc9bf75,0x3f7fbe95,0x3f093efc,0xbf583f5f,0x3e60bf77,0x3f7abe89,
0x3ecfbf7f,0x3f6abd97,0xbf6f3f42,0xbeb8bf27,0xbf7c3f1d,0xbe2fbf4a,0x3f513dfb,0xbf133f7e,0x3f313ea1,0xbf393f73,0x3cc9bf65,0x3f80bee6,
0x3f67bf5c,0x3edb3f04,0xbedbbf04,0x3f67bf5c,0xbf3ebe16,0x3f2cbf7d,0xbf2c3f7d,0xbf3ebe16,0xbeac3f78,0xbf713e79,0x3f71be79,0xbeac3f78,
0x3f80bf18,0x3d493f4e,0xbd49bf4e,0x3f80bf18,0xbea1bf09,0x3f73bf58,0xbf653e60,0x3ee6bf7a,0xbf5f3f6f,0xbefcbeb8,0xbe893f6a,0xbf773ecf,
0x3f273e2f,0xbf423f7c,0x3f7fbf13,0xbd973f51,0x3f1dbf80,0x3f4abcc9,0xbdfbbf31,0x3f7ebf39,0xbf7b3f55,0xbe48bf0e,0xbf7b3f55,0xbe48bf0e,
0x3e483f0e,0xbf7b3f55,0x3e483f0e,0xbf7b3f55,0x3f7bbf55,0x3e483f0e,0x3f7bbf55,0x3e483f0e,0xbe48bf0e,0x3f7bbf55,0xbe48bf0e,0x3f7bbf55,
0x3d973f13,0xbf7f3f51,0xbf273f7c,0xbf423e2f,0x3f7ebf31,0xbdfb3f39,0x3f1d3cc9,0xbf4a3f80,0x3ea1bf58,0x3f73bf09,0x3f65bf7a,0x3ee63e60,
0xbf5f3eb8,0x3efcbf6f,0xbe89becf,0x3f77bf6a,0x3f80bf4e,0xbd493f18,0xbd493f18,0xbf803f4e,0x3edbbf5c,0x3f67bf04,0x3f67bf04,0xbedb3f5c,
0xbf2c3e16,0x3f3ebf7d,0x3f3ebf7d,0x3f2cbe16,0xbf713f78,0xbeacbe79,0xbeacbe79,0x3f71bf78,0x3e2fbf1d,0x3f7cbf4a,0x3f13bdfb,0xbf513f7e,
0xbf393ea1,0x3f31bf73,0x3f80bf65,0x3cc93ee6,0xbf7a3f77,0xbe60be89,0x3f09bf5f,0x3f58befc,0xbeb83f42,0xbf6f3f27,0xbecfbd97,0x3f6abf7f,
0xbf753f46,0x3e95bf22,0x3f75bf46,0xbe953f22,0xbf623f7f,0xbef13dc9,0x3f62bf7f,0x3ef1bdc9,0xbe953f22,0xbf753f46,0x3e95bf22,0x3f75bf46,
0x3ef1bdc9,0xbf623f7f,0xbef13dc9,0x3f62bf7f,0xbecf3f27,0xbf6a3f42,0x3f6fbf7f,0x3eb8bd97,0x3e2f3dfb,0xbf7c3f7e,0x3f13bf4a,0x3f51bf1d,
0x3f31bee6,0xbf393f65,0x3cc9bea1,0x3f80bf73,0x3f7abf5f,0xbe603efc,0xbf093e89,0x3f58bf77,0x3f5cbf3e,0xbf043f2c,0x3f04bf2c,0x3f5cbf3e,
0x3f7dbf71,0xbe163eac,0x3e16beac,0x3f7dbf71,0x3f78bf80,0x3e79bd49,0xbe793d49,0x3f78bf80,0x3f4ebf67,0x3f18bedb,0xbf183edb,0x3f4ebf67,
0x3f1dbf31,0x3f4abf39,0xbdfb3cc9,0x3f7ebf80,0x3ee6bf09,0x3f65bf58,0xbea13e60,0x3f73bf7a,0x3e89beb8,0x3f77bf6f,0xbefc3ecf,0x3f5fbf6a,
0x3d97be2f,0x3f7fbf7c,0xbf273f13,0x3f42bf51,0x3f803f80,0xbf803f80,0x3f803f80,0xbf803f80,0x3f803f80,0xbf803f80,0x3f803f80,0xbf803f80,
0x3f803f80,0xbf803f80,0x3f803f80,0xbf803f80,0x3f803f80,0xbf803f80,0x3f803f80,0xbf803f80,0x3f7d3f80,0xbe16bd49,0x3f183f2c,0xbf4ebf3e,
0x3f713f78,0xbeacbe79,0x3edb3f04,0xbf67bf5c,0x3f5c3f67,0xbf04bedb,0x3e793eac,0xbf78bf71,0x3f3e3f4e,0xbf2cbf18,0x3d493e16,0xbf80bf7d,
0x3f753f7f,0xbe95bdc9,0xbe95bdc9,0xbf75bf7f,0x3f463f62,0xbf22bef1,0xbf22bef1,0xbf46bf62,0x3ef13f22,0xbf62bf46,0xbf62bf46,0xbef1bf22,
0x3dc93e95,0xbf7fbf75,0xbf7fbf75,0xbdc9be95,0x3f673f7d,0xbedbbe16,0xbf71bf4e,0xbeacbf18,0x3f043f3e,0xbf5cbf2c,0xbf78bf80,0x3e79bd49,
0xbd493e79,0xbf80bf78,0xbf2cbf5c,0x3f3e3f04,0xbf18beac,0xbf4ebf71,0xbe16bedb,0x3f7d3f67,0x3f553f7b,0xbf0ebe48,0xbf55bf7b,0x3f0e3e48,
0x3e483f0e,0xbf7bbf55,0xbe48bf0e,0x3f7b3f55,0xbf0ebe48,0xbf55bf7b,0x3f0e3e48,0x3f553f7b,0xbf7bbf55,0xbe48bf0e,0x3f7b3f55,0x3e483f0e,
0x3f3e3f78,0xbf2cbe79,0xbd49bf04,0x3f803f5c,0xbe163eac,0xbf7dbf71,0x3f4e3edb,0x3f183f67,0xbf67bf18,0xbedbbf4e,0x3f713f7d,0xbeac3e16,
0xbf5cbf80,0x3f043d49,0x3e793f2c,0xbf78bf3e,0x3f223f75,0xbf46be95,0x3f463e95,0x3f223f75,0xbef13dc9,0xbf62bf7f,0x3f623f7f,0xbef13dc9,
0xbf7fbf62,0x3dc9bef1,0xbdc93ef1,0xbf7fbf62,0xbe95bf46,0x3f753f22,0xbf75bf22,0xbe95bf46,0x3f043f71,0xbf5cbeac,0x3f783f67,0xbe793edb,
0xbf3ebe16,0xbf2cbf7d,0xbd493f18,0xbf80bf4e,0xbf4ebf80,0x3f18bd49,0xbf7dbf2c,0xbe16bf3e,0x3edbbe79,0x3f673f78,0xbeacbf5c,0x3f713f04,
0x3ec43f6d,0xbf6dbec4,0x3ec43f6d,0xbf6dbec4,0xbf6dbec4,0xbec4bf6d,0xbf6dbec4,0xbec4bf6d,0xbec4bf6d,0x3f6d3ec4,0xbec4bf6d,0x3f6d3ec4,
0x3f6d3ec4,0x3ec43f6d,0x3f6d3ec4,0x3ec43f6d,0x3e793f67,0xbf78bedb,0xbf043eac,0xbf5cbf71,0xbf80bf18,0xbd49bf4e,0xbf3ebf7d,0x3f2cbe16,
0x3e16bf2c,0x3f7d3f3e,0x3f4e3d49,0x3f183f80,0x3f713f5c,0xbeac3f04,0x3edb3f78,0xbf67be79,0x3dc93f62,0xbf7fbef1,0xbf7fbef1,0xbdc9bf62,
0xbf75bf46,0x3e95bf22,0x3e95bf22,0x3f753f46,0x3f22be95,0x3f463f75,0x3f463f75,0xbf223e95,0x3ef13f7f,0xbf62bdc9,0xbf62bdc9,0xbef1bf7f,
0xbd493f5c,0xbf80bf04,0xbf2cbf78,0x3f3ebe79,0xbf4ebf67,0x3f18bedb,0x3f7d3eac,0x3e163f71,0x3f713e16,0x3eac3f7d,0xbedb3f18,0xbf67bf4e,
0xbe793f3e,0xbf78bf2c,0xbf04bf80,0x3f5cbd49,0xbe483f55,0xbf7bbf0e,0x3e48bf55,0x3f7b3f0e,0xbf0ebf7b,0x3f55be48,0x3f0e3f7b,0xbf553e48,
0x3f7b3f0e,0xbe483f55,0xbf7bbf0e,0x3e48bf55,0xbf553e48,0xbf0ebf7b,0x3f55be48,0x3f0e3f7b,0xbeac3f4e,0xbf71bf18,0x3f67be16,0x3edb3f7d,
0xbe79bf80,0x3f783d49,0xbf043f2c,0xbf5cbf3e,0x3f3e3f5c,0xbf2c3f04,0xbd49bf78,0x3f803e79,0xbf7dbedb,0x3e16bf67,0x3f183f71,0xbf4e3eac,
0xbef13f46,0xbf62bf22,0x3f623f22,0xbef13f46,0x3dc9bf75,0x3f7f3e95,0xbf7fbe95,0x3dc9bf75,0x3e953f7f,0xbf753dc9,0x3f75bdc9,0x3e953f7f,
0xbf22bf62,0x3f46bef1,0xbf463ef1,0xbf22bf62,0xbf183f3e,0xbf4ebf2c,0x3e163f80,0xbf7d3d49,0x3edbbf5c,0x3f673f04,0xbeacbf78,0x3f71be79,
0xbe793f71,0xbf78beac,0x3f043f67,0xbf5c3edb,0x3d49bf7d,0x3f803e16,0xbf2cbf4e,0x3f3ebf18,0xbf353f35,0xbf35bf35,0xbf353f35,0xbf35bf35,
0x3f35bf35,0x3f353f35,0x3f35bf35,0x3f353f35,0xbf353f35,0xbf35bf35,0xbf353f35,0xbf35bf35,0x3f35bf35,0x3f353f35,0x3f35bf35,0x3f353f35,
0xbf4e3f2c,0xbf18bf3e,0xbf7dbd49,0x3e16bf80,0x3f67bf04,0x3edb3f5c,0x3f713e79,0xbeac3f78,0xbf783eac,0xbe79bf71,0xbf5cbedb,0x3f04bf67,
0x3f80be16,0x3d493f7d,0x3f3e3f18,0xbf2c3f4e,0xbf623f22,0xbef1bf46,0xbef1bf46,0x3f62bf22,0x3f7fbe95,0x3dc93f75,0x3dc93f75,0xbf7f3e95,
0xbf75bdc9,0x3e95bf7f,0x3e95bf7f,0x3f753dc9,0x3f463ef1,0xbf223f62,0xbf223f62,0xbf46bef1,0xbf713f18,0xbeacbf4e,0x3edbbf7d,0x3f673e16,
0x3f78bd49,0xbe793f80,0xbf5c3f3e,0xbf04bf2c,0xbf2cbf04,0x3f3ebf5c,0x3f80be79,0xbd493f78,0x3e163f67,0xbf7d3edb,0xbf4ebeac,0x3f18bf71,
0xbf7b3f0e,0xbe48bf55,0x3f7bbf0e,0x3e483f55,0x3f553e48,0xbf0e3f7b,0xbf55be48,0x3f0ebf7b,0xbe48bf55,0x3f7bbf0e,0x3e483f55,0xbf7b3f0e,
0xbf0e3f7b,0xbf55be48,0x3f0ebf7b,0x3f553e48,0xbf803f04,0xbd49bf5c,0x3f3e3e79,0xbf2c3f78,0x3f183edb,0xbf4e3f67,0x3e16bf71,0x3f7dbeac,
0x3eacbf7d,0x3f71be16,0xbf673f4e,0xbedbbf18,0xbf783f2c,0xbe79bf3e,0x3f5c3d49,0xbf043f80,0xbf7f3ef1,0x3dc9bf62,0xbdc93f62,0xbf7f3ef1,
0x3e953f22,0xbf753f46,0x3f75bf46,0x3e953f22,0x3f46bf75,0x3f223e95,0xbf22be95,0x3f46bf75,0xbf623dc9,0x3ef1bf7f,0xbef13f7f,0xbf623dc9,
0xbf783edb,0x3e79bf67,0xbf5c3f71,0xbf04beac,0xbd493f4e,0xbf803f18,0x3f2c3e16,0xbf3e3f7d,0x3f7dbf3e,0x3e163f2c,0x3f18bf80,0x3f4ebd49,
0xbeacbf04,0x3f71bf5c,0xbf673e79,0x3edbbf78,0xbf6d3ec4,0x3ec4bf6d,0xbf6d3ec4,0x3ec4bf6d,0xbec43f6d,0xbf6d3ec4,0xbec43f6d,0xbf6d3ec4,
0x3f6dbec4,0xbec43f6d,0x3f6dbec4,0xbec43f6d,0x3ec4bf6d,0x3f6dbec4,0x3ec4bf6d,0x3f6dbec4,0xbf5c3eac,0x3f04bf71,0xbe79bedb,0x3f78bf67,
0xbf2c3f7d,0xbf3e3e16,0xbf803f4e,0xbd49bf18,0x3f183d49,0xbf4e3f80,0xbe163f3e,0xbf7d3f2c,0x3f67bf78,0x3edb3e79,0x3f71bf04,0xbeac3f5c,
0xbf463e95,0x3f22bf75,0x3f22bf75,0x3f46be95,0xbf623f7f,0xbef1bdc9,0xbef1bdc9,0x3f62bf7f,0x3dc93ef1,0xbf7f3f62,0xbf7f3f62,0xbdc9bef1,
0x3f75bf22,0xbe953f46,0xbe953f46,0xbf753f22,0xbf2c3e79,0x3f3ebf78,0x3f80bf5c,0xbd493f04,0xbf7d3f71,0xbe16beac,0x3f18bf67,0x3f4ebedb,
0xbedb3f4e,0xbf673f18,0xbeacbe16,0x3f71bf7d,0x3f04bd49,0xbf5c3f80,0xbf783f3e,0x3e79bf2c,0xbf0e3e48,0x3f55bf7b,0x3f0ebe48,0xbf553f7b,
0xbf7b3f55,0x3e48bf0e,0x3f7bbf55,0xbe483f0e,0xbf553f7b,0xbf0e3e48,0x3f55bf7b,0x3f0ebe48,0xbe483f0e,0xbf7b3f55,0x3e48bf0e,0x3f7bbf55,
0xbedb3e16,0x3f67bf7d,0xbeac3f18,0xbf713f4e,0xbf5c3f2c,0x3f04bf3e,0x3e793d49,0xbf783f80,0xbf803f78,0xbd49be79,0x3f3ebf04,0xbf2c3f5c,
0xbf4e3f71,0xbf183eac,0x3f7dbf67,0xbe163edb,0xbe953dc9,0x3f75bf7f,0xbf753f7f,0xbe953dc9,0xbf223ef1,0x3f46bf62,0xbf463f62,0xbf223ef1,
0xbf623f46,0x3ef1bf22,0xbef13f22,0xbf623f46,0xbf7f3f75,0x3dc9be95,0xbdc93e95,0xbf7f3f75,0xbe163d49,0x3f7dbf80,0xbf4e3f3e,0x3f18bf2c,
0xbeac3e79,0x3f71bf78,0xbf673f5c,0x3edbbf04,0xbf043edb,0x3f5cbf67,0xbf783f71,0x3e79beac,0xbf2c3f18,0x3f3ebf4e,0xbf803f7d,0x3d49be16,
0x3f803f80,0xbf803f80,0x3f803f80,0xbf803f80,0x3f803f80,0xbf803f80,0x3f803f80,0xbf803f80,0x3f803f80,0xbf803f80,0x3f803f80,0xbf803f80,
0x3f803f80,0xbf803f80,0x3f803f80,0xbf803f80,0xbe16bd49,0xbf7dbf80,0xbf4ebf3e,0xbf18bf2c,0xbeacbe79,0xbf71bf78,0xbf67bf5c,0xbedbbf04,
0xbf04bedb,0xbf5cbf67,0xbf78bf71,0xbe79beac,0xbf2cbf18,0xbf3ebf4e,0xbf80bf7d,0xbd49be16,0xbf75bf7f,0x3e953dc9,0x3e953dc9,0x3f753f7f,
0xbf46bf62,0x3f223ef1,0x3f223ef1,0x3f463f62,0xbef1bf22,0x3f623f46,0x3f623f46,0x3ef13f22,0xbdc9be95,0x3f7f3f75,0x3f7f3f75,0x3dc93e95,
0x3edb3e16,0x3f673f7d,0x3eac3f18,0xbf71bf4e,0x3f5c3f2c,0x3f043f3e,0xbe793d49,0xbf78bf80,0x3f803f78,0xbd493e79,0xbf3ebf04,0xbf2cbf5c,
0x3f4e3f71,0xbf18beac,0xbf7dbf67,0xbe16bedb,0x3f553f7b,0xbf0ebe48,0xbf55bf7b,0x3f0e3e48,0x3e483f0e,0xbf7bbf55,0xbe48bf0e,0x3f7b3f55,
0xbf0ebe48,0xbf55bf7b,0x3f0e3e48,0x3f553f7b,0xbf7bbf55,0xbe48bf0e,0x3f7b3f55,0x3e483f0e,0xbf2cbe79,0xbf3ebf78,0x3f803f5c,0x3d493f04,
0xbf7dbf71,0x3e16beac,0x3f183f67,0xbf4ebedb,0xbedbbf4e,0x3f673f18,0xbeac3e16,0xbf71bf7d,0x3f043d49,0x3f5c3f80,0xbf78bf3e,0xbe79bf2c,
0xbf22bf75,0x3f463e95,0xbf46be95,0xbf22bf75,0x3ef1bdc9,0x3f623f7f,0xbf62bf7f,0x3ef1bdc9,0x3f7f3f62,0xbdc93ef1,0x3dc9bef1,0x3f7f3f62,
0x3e953f46,0xbf75bf22,0x3f753f22,0x3e953f46,0x3f5c3eac,0x3f043f71,0x3e79bedb,0x3f783f67,0x3f2c3f7d,0xbf3ebe16,0x3f803f4e,0xbd493f18,
0xbf183d49,0xbf4ebf80,0x3e163f3e,0xbf7dbf2c,0xbf67bf78,0x3edbbe79,0xbf71bf04,0xbeacbf5c,0x3ec43f6d,0xbf6dbec4,0x3ec43f6d,0xbf6dbec4,
0xbf6dbec4,0xbec4bf6d,0xbf6dbec4,0xbec4bf6d,0xbec4bf6d,0x3f6d3ec4,0xbec4bf6d,0x3f6d3ec4,0x3f6d3ec4,0x3ec43f6d,0x3f6d3ec4,0x3ec43f6d,
0xbf78bedb,0xbe79bf67,0xbf5cbf71,0x3f04beac,0xbd49bf4e,0x3f803f18,0x3f2cbe16,0x3f3e3f7d,0x3f7d3f3e,0xbe163f2c,0x3f183f80,0xbf4ebd49,
0xbeac3f04,0xbf71bf5c,0xbf67be79,0xbedbbf78,0xbdc9bf62,0x3f7f3ef1,0x3f7f3ef1,0x3dc93f62,0x3f753f46,0xbe953f22,0xbe953f22,0xbf75bf46,
0xbf223e95,0xbf46bf75,0xbf46bf75,0x3f22be95,0xbef1bf7f,0x3f623dc9,0x3f623dc9,0x3ef13f7f,0x3f803f04,0xbd493f5c,0xbf3e3e79,0xbf2cbf78,
0xbf183edb,0xbf4ebf67,0xbe16bf71,0x3f7d3eac,0xbeacbf7d,0x3f713e16,0x3f673f4e,0xbedb3f18,0x3f783f2c,0xbe793f3e,0xbf5c3d49,0xbf04bf80,
0xbe483f55,0xbf7bbf0e,0x3e48bf55,0x3f7b3f0e,0xbf0ebf7b,0x3f55be48,0x3f0e3f7b,0xbf553e48,0x3f7b3f0e,0xbe483f55,0xbf7bbf0e,0x3e48bf55,
0xbf553e48,0xbf0ebf7b,0x3f55be48,0x3f0e3f7b,0xbf71bf18,0x3eacbf4e,0x3edb3f7d,0xbf673e16,0x3f783d49,0x3e793f80,0xbf5cbf3e,0x3f04bf2c,
0xbf2c3f04,0xbf3ebf5c,0x3f803e79,0x3d493f78,0x3e16bf67,0x3f7d3edb,0xbf4e3eac,0xbf18bf71,0x3ef1bf46,0x3f623f22,0xbf62bf22,0x3ef1bf46,
0xbdc93f75,0xbf7fbe95,0x3f7f3e95,0xbdc93f75,0xbe95bf7f,0x3f75bdc9,0xbf753dc9,0xbe95bf7f,0x3f223f62,0xbf463ef1,0x3f46bef1,0x3f223f62,
0x3f4e3f2c,0xbf183f3e,0x3f7dbd49,0x3e163f80,0xbf67bf04,0x3edbbf5c,0xbf713e79,0xbeacbf78,0x3f783eac,0xbe793f71,0x3f5cbedb,0x3f043f67,
0xbf80be16,0x3d49bf7d,0xbf3e3f18,0xbf2cbf4e,0xbf353f35,0xbf35bf35,0xbf353f35,0xbf35bf35,0x3f35bf35,0x3f353f35,0x3f35bf35,0x3f353f35,
0xbf353f35,0xbf35bf35,0xbf353f35,0xbf35bf35,0x3f35bf35,0x3f353f35,0x3f35bf35,0x3f353f35,0xbf18bf3e,0x3f4ebf2c,0x3e16bf80,0x3f7d3d49,
0x3edb3f5c,0xbf673f04,0xbeac3f78,0xbf71be79,0xbe79bf71,0x3f78beac,0x3f04bf67,0x3f5c3edb,0x3d493f7d,0xbf803e16,0xbf2c3f4e,0xbf3ebf18,
0x3f62bf22,0x3ef13f46,0x3ef13f46,0xbf623f22,0xbf7f3e95,0xbdc9bf75,0xbdc9bf75,0x3f7fbe95,0x3f753dc9,0xbe953f7f,0xbe953f7f,0xbf75bdc9,
0xbf46bef1,0x3f22bf62,0x3f22bf62,0x3f463ef1,0x3eac3f4e,0xbf713f18,0xbf67be16,0x3edbbf7d,0x3e79bf80,0x3f78bd49,0x3f043f2c,0xbf5c3f3e,
0xbf3e3f5c,0xbf2cbf04,0x3d49bf78,0x3f80be79,0x3f7dbedb,0x3e163f67,0xbf183f71,0xbf4ebeac,0xbf7b3f0e,0xbe48bf55,0x3f7bbf0e,0x3e483f55,
0x3f553e48,0xbf0e3f7b,0xbf55be48,0x3f0ebf7b,0xbe48bf55,0x3f7bbf0e,0x3e483f55,0xbf7b3f0e,0xbf0e3f7b,0xbf55be48,0x3f0ebf7b,0x3f553e48,
0xbd49bf5c,0x3f80bf04,0xbf2c3f78,0xbf3ebe79,0xbf4e3f67,0xbf18bedb,0x3f7dbeac,0xbe163f71,0x3f71be16,0xbeac3f7d,0xbedbbf18,0x3f67bf4e,
0xbe79bf3e,0x3f78bf2c,0xbf043f80,0xbf5cbd49,0x3f7fbef1,0xbdc93f62,0x3dc9bf62,0x3f7fbef1,0xbe95bf22,0x3f75bf46,0xbf753f46,0xbe95bf22,
0xbf463f75,0xbf22be95,0x3f223e95,0xbf463f75,0x3f62bdc9,0xbef13f7f,0x3ef1bf7f,0x3f62bdc9,0xbe793f67,0xbf783edb,0x3f043eac,0xbf5c3f71,
0x3f80bf18,0xbd493f4e,0x3f3ebf7d,0x3f2c3e16,0xbe16bf2c,0x3f7dbf3e,0xbf4e3d49,0x3f18bf80,0xbf713f5c,0xbeacbf04,0xbedb3f78,0xbf673e79,
0xbf6d3ec4,0x3ec4bf6d,0xbf6d3ec4,0x3ec4bf6d,0xbec43f6d,0xbf6d3ec4,0xbec43f6d,0xbf6d3ec4,0x3f6dbec4,0xbec43f6d,0x3f6dbec4,0xbec43f6d,
0x3ec4bf6d,0x3f6dbec4,0x3ec4bf6d,0x3f6dbec4,0x3f04bf71,0x3f5cbeac,0x3f78bf67,0x3e793edb,0xbf3e3e16,0x3f2cbf7d,0xbd49bf18,0x3f80bf4e,
0xbf4e3f80,0xbf18bd49,0xbf7d3f2c,0x3e16bf3e,0x3edb3e79,0xbf673f78,0xbeac3f5c,0xbf713f04,0x3f46be95,0xbf223f75,0xbf223f75,0xbf463e95,
0x3f62bf7f,0x3ef13dc9,0x3ef13dc9,0xbf623f7f,0xbdc9bef1,0x3f7fbf62,0x3f7fbf62,0x3dc93ef1,0xbf753f22,0x3e95bf46,0x3e95bf46,0x3f75bf22,
0xbf3e3f78,0xbf2c3e79,0x3d49bf04,0x3f80bf5c,0x3e163eac,0xbf7d3f71,0xbf4e3edb,0x3f18bf67,0x3f67bf18,0xbedb3f4e,0xbf713f7d,0xbeacbe16,
0x3f5cbf80,0x3f04bd49,0xbe793f2c,0xbf783f3e,0xbf0e3e48,0x3f55bf7b,0x3f0ebe48,0xbf553f7b,0xbf7b3f55,0x3e48bf0e,0x3f7bbf55,0xbe483f0e,
0xbf553f7b,0xbf0e3e48,0x3f55bf7b,0x3f0ebe48,0xbe483f0e,0xbf7b3f55,0x3e48bf0e,0x3f7bbf55,0x3f67bf7d,0x3edbbe16,0xbf713f4e,0x3eacbf18,
0x3f04bf3e,0x3f5cbf2c,0xbf783f80,0xbe79bd49,0xbd49be79,0x3f80bf78,0xbf2c3f5c,0xbf3e3f04,0xbf183eac,0x3f4ebf71,0xbe163edb,0xbf7d3f67,
0x3e95bdc9,0xbf753f7f,0x3f75bf7f,0x3e95bdc9,0x3f22bef1,0xbf463f62,0x3f46bf62,0x3f22bef1,0x3f62bf46,0xbef13f22,0x3ef1bf22,0x3f62bf46,
0x3f7fbf75,0xbdc93e95,0x3dc9be95,0x3f7fbf75,0xbf7d3f80,0xbe163d49,0xbf183f2c,0xbf4e3f3e,0xbf713f78,0xbeac3e79,0xbedb3f04,0xbf673f5c,
0xbf5c3f67,0xbf043edb,0xbe793eac,0xbf783f71,0xbf3e3f4e,0xbf2c3f18,0xbd493e16,0xbf803f7d,0x3f803f80,0xbf803f80,0x3f803f80,0xbf803f80,
0x3f803f80,0xbf803f80,0x3f803f80,0xbf803f80,0x3f803f80,0xbf803f80,0x3f803f80,0xbf803f80,0x3f803f80,0xbf803f80,0x3f803f80,0xbf803f80,
0xbf7dbf80,0x3e163d49,0xbf18bf2c,0x3f4e3f3e,0xbf71bf78,0x3eac3e79,0xbedbbf04,0x3f673f5c,0xbf5cbf67,0x3f043edb,0xbe79beac,0x3f783f71,
0xbf3ebf4e,0x3f2c3f18,0xbd49be16,0x3f803f7d,0x3f753f7f,0xbe95bdc9,0xbe95bdc9,0xbf75bf7f,0x3f463f62,0xbf22bef1,0xbf22bef1,0xbf46bf62,
0x3ef13f22,0xbf62bf46,0xbf62bf46,0xbef1bf22,0x3dc93e95,0xbf7fbf75,0xbf7fbf75,0xbdc9be95,0xbf67bf7d,0x3edb3e16,0x3f713f4e,0x3eac3f18,
0xbf04bf3e,0x3f5c3f2c,0x3f783f80,0xbe793d49,0x3d49be79,0x3f803f78,0x3f2c3f5c,0xbf3ebf04,0x3f183eac,0x3f4e3f71,0x3e163edb,0xbf7dbf67,
0x3f553f7b,0xbf0ebe48,0xbf55bf7b,0x3f0e3e48,0x3e483f0e,0xbf7bbf55,0xbe48bf0e,0x3f7b3f55,0xbf0ebe48,0xbf55bf7b,0x3f0e3e48,0x3f553f7b,
0xbf7bbf55,0xbe48bf0e,0x3f7b3f55,0x3e483f0e,0xbf3ebf78,0x3f2c3e79,0x3d493f04,0xbf80bf5c,0x3e16beac,0x3f7d3f71,0xbf4ebedb,0xbf18bf67,
0x3f673f18,0x3edb3f4e,0xbf71bf7d,0x3eacbe16,0x3f5c3f80,0xbf04bd49,0xbe79bf2c,0x3f783f3e,0x3f223f75,0xbf46be95,0x3f463e95,0x3f223f75,
0xbef13dc9,0xbf62bf7f,0x3f623f7f,0xbef13dc9,0xbf7fbf62,0x3dc9bef1,0xbdc93ef1,0xbf7fbf62,0xbe95bf46,0x3f753f22,0xbf75bf22,0xbe95bf46,
0xbf04bf71,0x3f5c3eac,0xbf78bf67,0x3e79bedb,0x3f3e3e16,0x3f2c3f7d,0x3d49bf18,0x3f803f4e,0x3f4e3f80,0xbf183d49,0x3f7d3f2c,0x3e163f3e,
0xbedb3e79,0xbf67bf78,0x3eac3f5c,0xbf71bf04,0x3ec43f6d,0xbf6dbec4,0x3ec43f6d,0xbf6dbec4,0xbf6dbec4,0xbec4bf6d,0xbf6dbec4,0xbec4bf6d,
0xbec4bf6d,0x3f6d3ec4,0xbec4bf6d,0x3f6d3ec4,0x3f6d3ec4,0x3ec43f6d,0x3f6d3ec4,0x3ec43f6d,0xbe79bf67,0x3f783edb,0x3f04beac,0x3f5c3f71,
0x3f803f18,0x3d493f4e,0x3f3e3f7d,0xbf2c3e16,0xbe163f2c,0xbf7dbf3e,0xbf4ebd49,0xbf18bf80,0xbf71bf5c,0x3eacbf04,0xbedbbf78,0x3f673e79,
0x3dc93f62,0xbf7fbef1,0xbf7fbef1,0xbdc9bf62,0xbf75bf46,0x3e95bf22,0x3e95bf22,0x3f753f46,0x3f22be95,0x3f463f75,0x3f463f75,0xbf223e95,
0x3ef13f7f,0xbf62bdc9,0xbf62bdc9,0xbef1bf7f,0x3d49bf5c,0x3f803f04,0x3f2c3f78,0xbf3e3e79,0x3f4e3f67,0xbf183edb,0xbf7dbeac,0xbe16bf71,
0xbf71be16,0xbeacbf7d,0x3edbbf18,0x3f673f4e,0x3e79bf3e,0x3f783f2c,0x3f043f80,0xbf5c3d49,0xbe483f55,0xbf7bbf0e,0x3e48bf55,0x3f7b3f0e,
0xbf0ebf7b,0x3f55be48,0x3f0e3f7b,0xbf553e48,0x3f7b3f0e,0xbe483f55,0xbf7bbf0e,0x3e48bf55,0xbf553e48,0xbf0ebf7b,0x3f55be48,0x3f0e3f7b,
0x3eacbf4e,0x3f713f18,0xbf673e16,0xbedbbf7d,0x3e793f80,0xbf78bd49,0x3f04bf2c,0x3f5c3f3e,0xbf3ebf5c,0x3f2cbf04,0x3d493f78,0xbf80be79,
0x3f7d3edb,0xbe163f67,0xbf18bf71,0x3f4ebeac,0xbef13f46,0xbf62bf22,0x3f623f22,0xbef13f46,0x3dc9bf75,0x3f7f3e95,0xbf7fbe95,0x3dc9bf75,
0x3e953f7f,0xbf753dc9,0x3f75bdc9,0x3e953f7f,0xbf22bf62,0x3f46bef1,0xbf463ef1,0xbf22bf62,0x3f18bf3e,0x3f4e3f2c,0xbe16bf80,0x3f7dbd49,
0xbedb3f5c,0xbf67bf04,0x3eac3f78,0xbf713e79,0x3e79bf71,0x3f783eac,0xbf04bf67,0x3f5cbedb,0xbd493f7d,0xbf80be16,0x3f2c3f4e,0xbf3e3f18,
0xbf353f35,0xbf35bf35,0xbf353f35,0xbf35bf35,0x3f35bf35,0x3f353f35,0x3f35bf35,0x3f353f35,0xbf353f35,0xbf35bf35,0xbf353f35,0xbf35bf35,
0x3f35bf35,0x3f353f35,0x3f35bf35,0x3f353f35,0x3f4ebf2c,0x3f183f3e,0x3f7d3d49,0xbe163f80,0xbf673f04,0xbedbbf5c,0xbf71be79,0x3eacbf78,
0x3f78beac,0x3e793f71,0x3f5c3edb,0xbf043f67,0xbf803e16,0xbd49bf7d,0xbf3ebf18,0x3f2cbf4e,0xbf623f22,0xbef1bf46,0xbef1bf46,0x3f62bf22,
0x3f7fbe95,0x3dc93f75,0x3dc93f75,0xbf7f3e95,0xbf75bdc9,0x3e95bf7f,0x3e95bf7f,0x3f753dc9,0x3f463ef1,0xbf223f62,0xbf223f62,0xbf46bef1,
0x3f71bf18,0x3eac3f4e,0xbedb3f7d,0xbf67be16,0xbf783d49,0x3e79bf80,0x3f5cbf3e,0x3f043f2c,0x3f2c3f04,0xbf3e3f5c,0xbf803e79,0x3d49bf78,
0xbe16bf67,0x3f7dbedb,0x3f4e3eac,0xbf183f71,0xbf7b3f0e,0xbe48bf55,0x3f7bbf0e,0x3e483f55,0x3f553e48,0xbf0e3f7b,0xbf55be48,0x3f0ebf7b,
0xbe48bf55,0x3f7bbf0e,0x3e483f55,0xbf7b3f0e,0xbf0e3f7b,0xbf55be48,0x3f0ebf7b,0x3f553e48,0x3f80bf04,0x3d493f5c,0xbf3ebe79,0x3f2cbf78,
0xbf18bedb,0x3f4ebf67,0xbe163f71,0xbf7d3eac,0xbeac3f7d,0xbf713e16,0x3f67bf4e,0x3edb3f18,0x3f78bf2c,0x3e793f3e,0xbf5cbd49,0x3f04bf80,
0xbf7f3ef1,0x3dc9bf62,0xbdc93f62,0xbf7f3ef1,0x3e953f22,0xbf753f46,0x3f75bf46,0x3e953f22,0x3f46bf75,0x3f223e95,0xbf22be95,0x3f46bf75,
0xbf623dc9,0x3ef1bf7f,0xbef13f7f,0xbf623dc9,0x3f78bedb,0xbe793f67,0x3f5cbf71,0x3f043eac,0x3d49bf4e,0x3f80bf18,0xbf2cbe16,0x3f3ebf7d,
0xbf7d3f3e,0xbe16bf2c,0xbf183f80,0xbf4e3d49,0x3eac3f04,0xbf713f5c,0x3f67be79,0xbedb3f78,0xbf6d3ec4,0x3ec4bf6d,0xbf6d3ec4,0x3ec4bf6d,
0xbec43f6d,0xbf6d3ec4,0xbec43f6d,0xbf6d3ec4,0x3f6dbec4,0xbec43f6d,0x3f6dbec4,0xbec43f6d,0x3ec4bf6d,0x3f6dbec4,0x3ec4bf6d,0x3f6dbec4,
0x3f5cbeac,0xbf043f71,0x3e793edb,0xbf783f67,0x3f2cbf7d,0x3f3ebe16,0x3f80bf4e,0x3d493f18,0xbf18bd49,0x3f4ebf80,0x3e16bf3e,0x3f7dbf2c,
0xbf673f78,0xbedbbe79,0xbf713f04,0x3eacbf5c,0xbf463e95,0x3f22bf75,0x3f22bf75,0x3f46be95,0xbf623f7f,0xbef1bdc9,0xbef1bdc9,0x3f62bf7f,
0x3dc93ef1,0xbf7f3f62,0xbf7f3f62,0xbdc9bef1,0x3f75bf22,0xbe953f46,0xbe953f46,0xbf753f22,0x3f2cbe79,0xbf3e3f78,0xbf803f5c,0x3d49bf04,
0x3f7dbf71,0x3e163eac,0xbf183f67,0xbf4e3edb,0x3edbbf4e,0x3f67bf18,0x3eac3e16,0xbf713f7d,0xbf043d49,0x3f5cbf80,0x3f78bf3e,0xbe793f2c,
0xbf0e3e48,0x3f55bf7b,0x3f0ebe48,0xbf553f7b,0xbf7b3f55,0x3e48bf0e,0x3f7bbf55,0xbe483f0e,0xbf553f7b,0xbf0e3e48,0x3f55bf7b,0x3f0ebe48,
0xbe483f0e,0xbf7b3f55,0x3e48bf0e,0x3f7bbf55,0x3edbbe16,0xbf673f7d,0x3eacbf18,0x3f71bf4e,0x3f5cbf2c,0xbf043f3e,0xbe79bd49,0x3f78bf80,
0x3f80bf78,0x3d493e79,0xbf3e3f04,0x3f2cbf5c,0x3f4ebf71,0x3f18beac,0xbf7d3f67,0x3e16bedb,0xbe953dc9,0x3f75bf7f,0xbf753f7f,0xbe953dc9,
0xbf223ef1,0x3f46bf62,0xbf463f62,0xbf223ef1,0xbf623f46,0x3ef1bf22,0xbef13f22,0xbf623f46,0xbf7f3f75,0x3dc9be95,0xbdc93e95,0xbf7f3f75,
0x3e16bd49,0xbf7d3f80,0x3f4ebf3e,0xbf183f2c,0x3eacbe79,0xbf713f78,0x3f67bf5c,0xbedb3f04,0x3f04bedb,0xbf5c3f67,0x3f78bf71,0xbe793eac,
0x3f2cbf18,0xbf3e3f4e,0x3f80bf7d,0xbd493e16,0x3f803f80,0xbf803f80,0x3f803f80,0xbf803f80,0x3f803f80,0xbf803f80,0x3f803f80,0xbf803f80,
0x3f803f80,0xbf803f80,0x3f803f80,0xbf803f80,0x3f803f80,0xbf803f80,0x3f803f80,0xbf803f80,0x3e163d49,0x3f7d3f80,0x3f4e3f3e,0x3f183f2c,
0x3eac3e79,0x3f713f78,0x3f673f5c,0x3edb3f04,0x3f043edb,0x3f5c3f67,0x3f783f71,0x3e793eac,0x3f2c3f18,0x3f3e3f4e,0x3f803f7d,0x3d493e16,
0xbf75bf7f,0x3e953dc9,0x3e953dc9,0x3f753f7f,0xbf46bf62,0x3f223ef1,0x3f223ef1,0x3f463f62,0xbef1bf22,0x3f623f46,0x3f623f46,0x3ef13f22,
0xbdc9be95,0x3f7f3f75,0x3f7f3f75,0x3dc93e95,0xbedbbe16,0xbf67bf7d,0xbeacbf18,0x3f713f4e,0xbf5cbf2c,0xbf04bf3e,0x3e79bd49,0x3f783f80,
0xbf80bf78,0x3d49be79,0x3f3e3f04,0x3f2c3f5c,0xbf4ebf71,0x3f183eac,0x3f7d3f67,0x3e163edb,0x3f553f7b,0xbf0ebe48,0xbf55bf7b,0x3f0e3e48,
0x3e483f0e,0xbf7bbf55,0xbe48bf0e,0x3f7b3f55,0xbf0ebe48,0xbf55bf7b,0x3f0e3e48,0x3f553f7b,0xbf7bbf55,0xbe48bf0e,0x3f7b3f55,0x3e483f0e,
0x3f2c3e79,0x3f3e3f78,0xbf80bf5c,0xbd49bf04,0x3f7d3f71,0xbe163eac,0xbf18bf67,0x3f4e3edb,0x3edb3f4e,0xbf67bf18,0x3eacbe16,0x3f713f7d,
0xbf04bd49,0xbf5cbf80,0x3f783f3e,0x3e793f2c,0xbf22bf75,0x3f463e95,0xbf46be95,0xbf22bf75,0x3ef1bdc9,0x3f623f7f,0xbf62bf7f,0x3ef1bdc9,
0x3f7f3f62,0xbdc93ef1,0x3dc9bef1,0x3f7f3f62,0x3e953f46,0xbf75bf22,0x3f753f22,0x3e953f46,0xbf5cbeac,0xbf04bf71,0xbe793edb,0xbf78bf67,
0xbf2cbf7d,0x3f3e3e16,0xbf80bf4e,0x3d49bf18,0x3f18bd49,0x3f4e3f80,0xbe16bf3e,0x3f7d3f2c,0x3f673f78,0xbedb3e79,0x3f713f04,0x3eac3f5c,
0x3ec43f6d,0xbf6dbec4,0x3ec43f6d,0xbf6dbec4,0xbf6dbec4,0xbec4bf6d,0xbf6dbec4,0xbec4bf6d,0xbec4bf6d,0x3f6d3ec4,0xbec4bf6d,0x3f6d3ec4,
0x3f6d3ec4,0x3ec43f6d,0x3f6d3ec4,0x3ec43f6d,0x3f783edb,0x3e793f67,0x3f5c3f71,0xbf043eac,0x3d493f4e,0xbf80bf18,0xbf2c3e16,0xbf3ebf7d,
0xbf7dbf3e,0x3e16bf2c,0xbf18bf80,0x3f4e3d49,0x3eacbf04,0x3f713f5c,0x3f673e79,0x3edb3f78,0xbdc9bf62,0x3f7f3ef1,0x3f7f3ef1,0x3dc93f62,
0x3f753f46,0xbe953f22,0xbe953f22,0xbf75bf46,0xbf223e95,0xbf46bf75,0xbf46bf75,0x3f22be95,0xbef1bf7f,0x3f623dc9,0x3f623dc9,0x3ef13f7f,
0xbf80bf04,0x3d49bf5c,0x3f3ebe79,0x3f2c3f78,0x3f18bedb,0x3f4e3f67,0x3e163f71,0xbf7dbeac,0x3eac3f7d,0xbf71be16,0xbf67bf4e,0x3edbbf18,
0xbf78bf2c,0x3e79bf3e,0x3f5cbd49,0x3f043f80,0xbe483f55,0xbf7bbf0e,0x3e48bf55,0x3f7b3f0e,0xbf0ebf7b,0x3f55be48,0x3f0e3f7b,0xbf553e48,
0x3f7b3f0e,0xbe483f55,0xbf7bbf0e,0x3e48bf55,0xbf553e48,0xbf0ebf7b,0x3f55be48,0x3f0e3f7b,0x3f713f18,0xbeac3f4e,0xbedbbf7d,0x3f67be16,
0xbf78bd49,0xbe79bf80,0x3f5c3f3e,0xbf043f2c,0x3f2cbf04,0x3f3e3f5c,0xbf80be79,0xbd49bf78,0xbe163f67,0xbf7dbedb,0x3f4ebeac,0x3f183f71,
0x3ef1bf46,0x3f623f22,0xbf62bf22,0x3ef1bf46,0xbdc93f75,0xbf7fbe95,0x3f7f3e95,0xbdc93f75,0xbe95bf7f,0x3f75bdc9,0xbf753dc9,0xbe95bf7f,
0x3f223f62,0xbf463ef1,0x3f46bef1,0x3f223f62,0xbf4ebf2c,0x3f18bf3e,0xbf7d3d49,0xbe16bf80,0x3f673f04,0xbedb3f5c,0x3f71be79,0x3eac3f78,
0xbf78beac,0x3e79bf71,0xbf5c3edb,0xbf04bf67,0x3f803e16,0xbd493f7d,0x3f3ebf18,0x3f2c3f4e,0xbf353f35,0xbf35bf35,0xbf353f35,0xbf35bf35,
0x3f35bf35,0x3f353f35,0x3f35bf35,0x3f353f35,0xbf353f35,0xbf35bf35,0xbf353f35,0xbf35bf35,0x3f35bf35,0x3f353f35,0x3f35bf35,0x3f353f35,
0x3f183f3e,0xbf4e3f2c,0xbe163f80,0xbf7dbd49,0xbedbbf5c,0x3f67bf04,0x3eacbf78,0x3f713e79,0x3e793f71,0xbf783eac,0xbf043f67,0xbf5cbedb,
0xbd49bf7d,0x3f80be16,0x3f2cbf4e,0x3f3e3f18,0x3f62bf22,0x3ef13f46,0x3ef13f46,0xbf623f22,0xbf7f3e95,0xbdc9bf75,0xbdc9bf75,0x3f7fbe95,
0x3f753dc9,0xbe953f7f,0xbe953f7f,0xbf75bdc9,0xbf46bef1,0x3f22bf62,0x3f22bf62,0x3f463ef1,0xbeacbf4e,0x3f71bf18,0x3f673e16,0xbedb3f7d,
0xbe793f80,0xbf783d49,0xbf04bf2c,0x3f5cbf3e,0x3f3ebf5c,0x3f2c3f04,0xbd493f78,0xbf803e79,0xbf7d3edb,0xbe16bf67,0x3f18bf71,0x3f4e3eac,
0xbf7b3f0e,0xbe48bf55,0x3f7bbf0e,0x3e483f55,0x3f553e48,0xbf0e3f7b,0xbf55be48,0x3f0ebf7b,0xbe48bf55,0x3f7bbf0e,0x3e483f55,0xbf7b3f0e,
0xbf0e3f7b,0xbf55be48,0x3f0ebf7b,0x3f553e48,0x3d493f5c,0xbf803f04,0x3f2cbf78,0x3f3e3e79,0x3f4ebf67,0x3f183edb,0xbf7d3eac,0x3e16bf71,
0xbf713e16,0x3eacbf7d,0x3edb3f18,0xbf673f4e,0x3e793f3e,0xbf783f2c,0x3f04bf80,0x3f5c3d49,0x3f7fbef1,0xbdc93f62,0x3dc9bf62,0x3f7fbef1,
0xbe95bf22,0x3f75bf46,0xbf753f46,0xbe95bf22,0xbf463f75,0xbf22be95,0x3f223e95,0xbf463f75,0x3f62bdc9,0xbef13f7f,0x3ef1bf7f,0x3f62bdc9,
0x3e79bf67,0x3f78bedb,0xbf04beac,0x3f5cbf71,0xbf803f18,0x3d49bf4e,0xbf3e3f7d,0xbf2cbe16,0x3e163f2c,0xbf7d3f3e,0x3f4ebd49,0xbf183f80,
0x3f71bf5c,0x3eac3f04,0x3edbbf78,0x3f67be79,0xbf6d3ec4,0x3ec4bf6d,0xbf6d3ec4,0x3ec4bf6d,0xbec43f6d,0xbf6d3ec4,0xbec43f6d,0xbf6d3ec4,
0x3f6dbec4,0xbec43f6d,0x3f6dbec4,0xbec43f6d,0x3ec4bf6d,0x3f6dbec4,0x3ec4bf6d,0x3f6dbec4,0xbf043f71,0xbf5c3eac,0xbf783f67,0xbe79bedb,
0x3f3ebe16,0xbf2c3f7d,0x3d493f18,0xbf803f4e,0x3f4ebf80,0x3f183d49,0x3f7dbf2c,0xbe163f3e,0xbedbbe79,0x3f67bf78,0x3eacbf5c,0x3f71bf04,
0x3f46be95,0xbf223f75,0xbf223f75,0xbf463e95,0x3f62bf7f,0x3ef13dc9,0x3ef13dc9,0xbf623f7f,0xbdc9bef1,0x3f7fbf62,0x3f7fbf62,0x3dc93ef1,
0xbf753f22,0x3e95bf46,0x3e95bf46,0x3f75bf22,0x3f3ebf78,0x3f2cbe79,0xbd493f04,0xbf803f5c,0xbe16beac,0x3f7dbf71,0x3f4ebedb,0xbf183f67,
0xbf673f18,0x3edbbf4e,0x3f71bf7d,0x3eac3e16,0xbf5c3f80,0xbf043d49,0x3e79bf2c,0x3f78bf3e,0xbf0e3e48,0x3f55bf7b,0x3f0ebe48,0xbf553f7b,
0xbf7b3f55,0x3e48bf0e,0x3f7bbf55,0xbe483f0e,0xbf553f7b,0xbf0e3e48,0x3f55bf7b,0x3f0ebe48,0xbe483f0e,0xbf7b3f55,0x3e48bf0e,0x3f7bbf55,
0xbf673f7d,0xbedb3e16,0x3f71bf4e,0xbeac3f18,0xbf043f3e,0xbf5c3f2c,0x3f78bf80,0x3e793d49,0x3d493e79,0xbf803f78,0x3f2cbf5c,0x3f3ebf04,
0x3f18beac,0xbf4e3f71,0x3e16bedb,0x3f7dbf67,0x3e95bdc9,0xbf753f7f,0x3f75bf7f,0x3e95bdc9,0x3f22bef1,0xbf463f62,0x3f46bf62,0x3f22bef1,
0x3f62bf46,0xbef13f22,0x3ef1bf22,0x3f62bf46,0x3f7fbf75,0xbdc93e95,0x3dc9be95,0x3f7fbf75,0x3f7dbf80,0x3e16bd49,0x3f18bf2c,0x3f4ebf3e,
0x3f71bf78,0x3eacbe79,0x3edbbf04,0x3f67bf5c,0x3f5cbf67,0x3f04bedb,0x3e79beac,0x3f78bf71,0x3f3ebf4e,0x3f2cbf18,0x3d49be16,0x3f80bf7d,
0x3f803f80,0xbf353f35,0x3f803f80,0xbf353f35,0x3f803f80,0xbf353f35,0x3f803f80,0xbf353f35,0x3f803f80,0xbf353f35,0x3f803f80,0xbf353f35,
0x3f803f80,0xbf353f35,0x3f803f80,0xbf353f35,0x3f7c3f7f,0xbe2fbd97,0x3f133f27,0xbf51bf42,0x3f6f3f77,0xbeb8be89,0x3ecf3efc,0xbf6abf5f,
0x3f583f65,0xbf09bee6,0x3e603ea1,0xbf7abf73,0x3f393f4a,0xbf31bf1d,0x3cc93dfb,0xbf80bf7e,0x3f713f7d,0xbeacbe16,0xbeacbe16,0xbf71bf7d,
0x3f3e3f5c,0xbf2cbf04,0xbf2cbf04,0xbf3ebf5c,0x3edb3f18,0xbf67bf4e,0xbf67bf4e,0xbedbbf18,0x3d493e79,0xbf80bf78,0xbf80bf78,0xbd49be79,
0x3f5f3f7a,0xbefcbe60,0xbf77bf58,0xbe89bf09,0x3ee63f31,0xbf65bf39,0xbf73bf80,0x3ea13cc9,0xbdfb3e2f,0xbf7ebf7c,0xbf1dbf51,0x3f4a3f13,
0xbf27becf,0xbf42bf6a,0xbd97beb8,0x3f7f3f6f,0x3f463f75,0xbf22be95,0xbf46bf75,0x3f223e95,0x3dc93ef1,0xbf7fbf62,0xbdc9bef1,0x3f7f3f62,
0xbf22be95,0xbf46bf75,0x3f223e95,0x3f463f75,0xbf7fbf62,0xbdc9bef1,0x3f7f3f62,0x3dc93ef1,0x3f273f6f,0xbf42beb8,0x3d97becf,0x3f7f3f6a,
0xbe893e60,0xbf77bf7a,0x3f5f3f09,0x3efc3f58,0xbf73bf31,0xbea1bf39,0x3f653f80,0xbee63cc9,0xbf4abf7c,0x3f1d3e2f,0x3dfb3f13,0xbf7ebf51,
0x3f043f67,0xbf5cbedb,0x3f5c3edb,0x3f043f67,0xbf18bd49,0xbf4ebf80,0x3f4e3f80,0xbf18bd49,0xbf78bf71,0x3e79beac,0xbe793eac,0xbf78bf71,
0xbe16bf2c,0x3f7d3f3e,0xbf7dbf3e,0xbe16bf2c,0x3eb83f5f,0xbf6fbefc,0x3f6a3f77,0xbecf3e89,0xbf58bea1,0xbf09bf73,0xbe603ee6,0xbf7abf65,
0xbf31bf7e,0x3f393dfb,0xbf80bf4a,0x3cc9bf1d,0x3f13bd97,0x3f513f7f,0xbe2fbf42,0x3f7c3f27,0x3e483f55,0xbf7bbf0e,0x3e483f55,0xbf7bbf0e,
0xbf7bbf0e,0xbe48bf55,0xbf7bbf0e,0xbe48bf55,0xbe48bf55,0x3f7b3f0e,0xbe48bf55,0x3f7b3f0e,0x3f7b3f0e,0x3e483f55,0x3f7b3f0e,0x3e483f55,
0x3cc93f4a,0xbf80bf1d,0xbf313dfb,0xbf39bf7e,0xbf7cbf42,0x3e2fbf27,0xbf13bf7f,0x3f513d97,0x3eb8befc,0x3f6f3f5f,0x3f6a3e89,0x3ecf3f77,
0x3f583f73,0xbf093ea1,0x3e603f65,0xbf7abee6,0xbe163f3e,0xbf7dbf2c,0xbf7dbf2c,0x3e16bf3e,0xbf5cbf67,0x3f04bedb,0x3f04bedb,0x3f5c3f67,
0x3f4ebd49,0x3f183f80,0x3f183f80,0xbf4e3d49,0x3e793f71,0xbf78beac,0xbf78beac,0xbe79bf71,0xbea13f31,0xbf73bf39,0xbee6bf80,0x3f653cc9,
0xbf1dbf7c,0x3f4abe2f,0x3f7e3f13,0xbdfb3f51,0x3f7f3ecf,0x3d973f6a,0xbf273eb8,0xbf42bf6f,0xbefc3f09,0xbf5fbf58,0xbe89bf7a,0x3f773e60,
0xbef13f22,0xbf62bf46,0x3ef1bf22,0x3f623f46,0xbe95bf7f,0x3f753dc9,0x3e953f7f,0xbf75bdc9,0x3f623f46,0xbef13f22,0xbf62bf46,0x3ef1bf22,
0xbf75bdc9,0xbe95bf7f,0x3f753dc9,0x3e953f7f,0xbf1d3f13,0xbf4abf51,0x3f7e3e2f,0x3dfb3f7c,0x3d97bf6f,0x3f7f3eb8,0xbf423ecf,0xbf27bf6a,
0x3efc3f7a,0xbf5f3e60,0x3e89bf58,0x3f773f09,0xbf65bf31,0x3ee6bf39,0x3ea13f80,0xbf733cc9,0xbf3e3f04,0xbf2cbf5c,0x3f2c3f5c,0xbf3e3f04,
0x3edbbf4e,0x3f673f18,0xbf67bf18,0x3edbbf4e,0xbd493f78,0xbf80be79,0x3f803e79,0xbd493f78,0xbeacbf7d,0x3f71be16,0xbf713e16,0xbeacbf7d,
0xbf583ee6,0xbf09bf65,0xbe603f73,0xbf7abea1,0x3f39bf1d,0x3f313f4a,0x3cc9bf7e,0x3f803dfb,0xbf133f42,0xbf51bf27,0x3e2f3f7f,0xbf7c3d97,
0x3ecfbf5f,0x3f6a3efc,0xbeb8bf77,0x3f6fbe89,0xbf6d3ec4,0xbec4bf6d,0xbf6d3ec4,0xbec4bf6d,0x3f6dbec4,0x3ec43f6d,0x3f6dbec4,0x3ec43f6d,
0xbf6d3ec4,0xbec4bf6d,0xbf6d3ec4,0xbec4bf6d,0x3f6dbec4,0x3ec43f6d,0x3f6dbec4,0x3ec43f6d,0xbf7a3ea1,0xbe60bf73,0xbf58bee6,0x3f09bf65,
0x3f80bdfb,0x3cc93f7e,0x3f393f1d,0xbf313f4a,0xbf7cbd97,0x3e2fbf7f,0xbf13bf42,0x3f51bf27,0x3f6f3e89,0xbeb83f77,0x3ecf3f5f,0xbf6a3efc,
0xbf803e79,0xbd49bf78,0xbd49bf78,0x3f80be79,0x3f713e16,0xbeac3f7d,0xbeac3f7d,0xbf71be16,0xbf3ebf04,0x3f2cbf5c,0x3f2cbf5c,0x3f3e3f04,
0x3edb3f4e,0xbf673f18,0xbf673f18,0xbedbbf4e,0xbf7e3e2f,0x3dfbbf7c,0x3f4abf51,0x3f1d3f13,0x3f423ecf,0xbf273f6a,0xbf7f3eb8,0xbd97bf6f,
0xbe89bf58,0x3f77bf09,0x3f5f3e60,0xbefc3f7a,0xbea13f80,0xbf73bcc9,0xbee6bf39,0x3f65bf31,0xbf753dc9,0x3e95bf7f,0x3f75bdc9,0xbe953f7f,
0x3ef13f22,0xbf623f46,0xbef1bf22,0x3f62bf46,0x3e95bf7f,0x3f75bdc9,0xbe953f7f,0xbf753dc9,0xbf623f46,0xbef1bf22,0x3f62bf46,0x3ef13f22,
0xbf653cc9,0x3ee6bf80,0x3ea13f31,0xbf733f39,0x3dfb3f51,0xbf7e3f13,0x3f1dbf7c,0x3f4a3e2f,0x3f42bf6f,0x3f273eb8,0xbf7f3ecf,0x3d97bf6a,
0xbf773e60,0x3e89bf7a,0x3efc3f09,0xbf5f3f58,0xbf4ebd49,0x3f18bf80,0xbf183f80,0xbf4ebd49,0xbe793f71,0xbf783eac,0x3f78beac,0xbe793f71,
0x3f7dbf2c,0x3e163f3e,0xbe16bf3e,0x3f7dbf2c,0xbf04bedb,0x3f5cbf67,0xbf5c3f67,0xbf04bedb,0xbf31bdfb,0x3f39bf7e,0xbf803f1d,0x3cc9bf4a,
0xbf133f7f,0xbf513d97,0x3e2f3f27,0xbf7c3f42,0x3f6abe89,0xbecf3f77,0x3f6fbf5f,0x3eb83efc,0x3e60bf65,0x3f7abee6,0xbf09bea1,0x3f58bf73,
0xbf0ebe48,0x3f55bf7b,0xbf0ebe48,0x3f55bf7b,0xbf553f7b,0xbf0ebe48,0xbf553f7b,0xbf0ebe48,0x3f0e3e48,0xbf553f7b,0x3f0e3e48,0xbf553f7b,
0x3f55bf7b,0x3f0e3e48,0x3f55bf7b,0x3f0e3e48,0xbecfbe89,0x3f6abf77,0x3eb8bf5f,0x3f6fbefc,0xbf7a3f65,0xbe60bee6,0xbf583ea1,0x3f09bf73,
0x3cc93f1d,0xbf803f4a,0xbf313f7e,0xbf393dfb,0x3f7cbf27,0xbe2f3f42,0x3f133d97,0xbf513f7f,0xbe79beac,0x3f78bf71,0x3f78bf71,0x3e793eac,
0xbf7d3f3e,0x3e16bf2c,0x3e16bf2c,0x3f7dbf3e,0xbf043f67,0xbf5c3edb,0xbf5c3edb,0x3f04bf67,0x3f18bd49,0xbf4e3f80,0xbf4e3f80,0xbf183d49,
0xbd97becf,0x3f7fbf6a,0x3f42beb8,0xbf273f6f,0xbf5f3f09,0x3efcbf58,0x3f77bf7a,0x3e893e60,0xbf653f80,0xbee6bcc9,0x3ea1bf39,0x3f73bf31,
0xbdfb3f13,0xbf7e3f51,0xbf1d3e2f,0x3f4abf7c,0x3dc9bef1,0x3f7fbf62,0xbdc93ef1,0xbf7f3f62,0xbf223e95,0x3f46bf75,0x3f22be95,0xbf463f75,
0xbf7f3f62,0x3dc9bef1,0x3f7fbf62,0xbdc93ef1,0xbf463f75,0xbf223e95,0x3f46bf75,0x3f22be95,0x3e89bf09,0x3f77bf58,0xbf5f3f7a,0xbefc3e60,
0xbea13cc9,0x3f73bf80,0xbee63f31,0xbf653f39,0xbf4a3f13,0x3f1dbf51,0x3dfb3e2f,0xbf7e3f7c,0xbf7f3f6f,0x3d97beb8,0x3f27becf,0xbf423f6a,
0x3edbbf18,0x3f67bf4e,0xbf673f4e,0x3edbbf18,0x3d49be79,0x3f80bf78,0xbf803f78,0x3d49be79,0xbeac3e16,0x3f71bf7d,0xbf713f7d,0xbeac3e16,
0xbf2c3f04,0x3f3ebf5c,0xbf3e3f5c,0xbf2c3f04,0x3f13bf27,0x3f51bf42,0xbe2f3d97,0x3f7cbf7f,0x3ecfbefc,0x3f6abf5f,0xbeb83e89,0x3f6fbf77,
0x3e60bea1,0x3f7abf73,0xbf093ee6,0x3f58bf65,0x3cc9bdfb,0x3f80bf7e,0xbf313f1d,0x3f39bf4a,0x3f803f80,0xbf353f35,0x3f803f80,0xbf353f35,
0x3f803f80,0xbf353f35,0x3f803f80,0xbf353f35,0x3f803f80,0xbf353f35,0x3f803f80,0xbf353f35,0x3f803f80,0xbf353f35,0x3f803f80,0xbf353f35,
0xbe2fbd97,0xbf7cbf7f,0xbf51bf42,0xbf13bf27,0xbeb8be89,0xbf6fbf77,0xbf6abf5f,0xbecfbefc,0xbf09bee6,0xbf58bf65,0xbf7abf73,0xbe60bea1,
0xbf31bf1d,0xbf39bf4a,0xbf80bf7e,0xbcc9bdfb,0xbf71bf7d,0x3eac3e16,0x3eac3e16,0x3f713f7d,0xbf3ebf5c,0x3f2c3f04,0x3f2c3f04,0x3f3e3f5c,
0xbedbbf18,0x3f673f4e,0x3f673f4e,0x3edb3f18,0xbd49be79,0x3f803f78,0x3f803f78,0x3d493e79,0x3efc3e60,0x3f5f3f7a,0x3e893f09,0xbf77bf58,
0x3f653f39,0x3ee63f31,0xbea1bcc9,0xbf73bf80,0x3f7e3f7c,0xbdfb3e2f,0xbf4abf13,0xbf1dbf51,0x3f423f6a,0xbf27becf,0xbf7fbf6f,0xbd97beb8,
0x3f463f75,0xbf22be95,0xbf46bf75,0x3f223e95,0x3dc93ef1,0xbf7fbf62,0xbdc9bef1,0x3f7f3f62,0xbf22be95,0xbf46bf75,0x3f223e95,0x3f463f75,
0xbf7fbf62,0xbdc9bef1,0x3f7f3f62,0x3dc93ef1,0xbf42beb8,0xbf27bf6f,0x3f7f3f6a,0xbd973ecf,0xbf77bf7a,0x3e89be60,0x3efc3f58,0xbf5fbf09,
0xbea1bf39,0x3f733f31,0xbee63cc9,0xbf65bf80,0x3f1d3e2f,0x3f4a3f7c,0xbf7ebf51,0xbdfbbf13,0xbf04bf67,0x3f5c3edb,0xbf5cbedb,0xbf04bf67,
0x3f183d49,0x3f4e3f80,0xbf4ebf80,0x3f183d49,0x3f783f71,0xbe793eac,0x3e79beac,0x3f783f71,0x3e163f2c,0xbf7dbf3e,0x3f7d3f3e,0x3e163f2c,
0x3f6f3efc,0x3eb83f5f,0x3ecfbe89,0x3f6a3f77,0x3f093f73,0xbf58bea1,0x3f7a3f65,0xbe603ee6,0xbf39bdfb,0xbf31bf7e,0xbcc93f1d,0xbf80bf4a,
0xbf51bf7f,0x3f13bd97,0xbf7cbf27,0xbe2fbf42,0x3e483f55,0xbf7bbf0e,0x3e483f55,0xbf7bbf0e,0xbf7bbf0e,0xbe48bf55,0xbf7bbf0e,0xbe48bf55,
0xbe48bf55,0x3f7b3f0e,0xbe48bf55,0x3f7b3f0e,0x3f7b3f0e,0x3e483f55,0x3f7b3f0e,0x3e483f55,0xbf80bf1d,0xbcc9bf4a,0xbf39bf7e,0x3f31bdfb,
0x3e2fbf27,0x3f7c3f42,0x3f513d97,0x3f133f7f,0x3f6f3f5f,0xbeb83efc,0x3ecf3f77,0xbf6abe89,0xbf093ea1,0xbf58bf73,0xbf7abee6,0xbe60bf65,
0x3e16bf3e,0x3f7d3f2c,0x3f7d3f2c,0xbe163f3e,0x3f5c3f67,0xbf043edb,0xbf043edb,0xbf5cbf67,0xbf4e3d49,0xbf18bf80,0xbf18bf80,0x3f4ebd49,
0xbe79bf71,0x3f783eac,0x3f783eac,0x3e793f71,0x3f733f39,0xbea13f31,0xbf65bcc9,0xbee6bf80,0xbf4a3e2f,0xbf1dbf7c,0x3dfbbf51,0x3f7e3f13,
0xbd97bf6a,0x3f7f3ecf,0x3f423f6f,0xbf273eb8,0x3f5f3f58,0xbefc3f09,0xbf77be60,0xbe89bf7a,0xbef13f22,0xbf62bf46,0x3ef1bf22,0x3f623f46,
0xbe95bf7f,0x3f753dc9,0x3e953f7f,0xbf75bdc9,0x3f623f46,0xbef13f22,0xbf62bf46,0x3ef1bf22,0xbf75bdc9,0xbe95bf7f,0x3f753dc9,0x3e953f7f,
0xbf4abf51,0x3f1dbf13,0x3dfb3f7c,0xbf7ebe2f,0x3f7f3eb8,0xbd973f6f,0xbf27bf6a,0x3f42becf,0xbf5f3e60,0xbefcbf7a,0x3f773f09,0xbe893f58,
0x3ee6bf39,0x3f653f31,0xbf733cc9,0xbea1bf80,0x3f3ebf04,0x3f2c3f5c,0xbf2cbf5c,0x3f3ebf04,0xbedb3f4e,0xbf67bf18,0x3f673f18,0xbedb3f4e,
0x3d49bf78,0x3f803e79,0xbf80be79,0x3d49bf78,0x3eac3f7d,0xbf713e16,0x3f71be16,0x3eac3f7d,0x3f093f65,0xbf583ee6,0x3f7a3ea1,0xbe603f73,
0xbf31bf4a,0x3f39bf1d,0xbf80bdfb,0x3cc9bf7e,0x3f513f27,0xbf133f42,0x3f7cbd97,0x3e2f3f7f,0xbf6abefc,0x3ecfbf5f,0xbf6f3e89,0xbeb8bf77,
0xbf6d3ec4,0xbec4bf6d,0xbf6d3ec4,0xbec4bf6d,0x3f6dbec4,0x3ec43f6d,0x3f6dbec4,0x3ec43f6d,0xbf6d3ec4,0xbec4bf6d,0xbf6d3ec4,0xbec4bf6d,
0x3f6dbec4,0x3ec43f6d,0x3f6dbec4,0x3ec43f6d,0xbe60bf73,0x3f7abea1,0x3f09bf65,0x3f583ee6,0x3cc93f7e,0xbf803dfb,0xbf313f4a,0xbf39bf1d,
0x3e2fbf7f,0x3f7c3d97,0x3f51bf27,0x3f133f42,0xbeb83f77,0xbf6fbe89,0xbf6a3efc,0xbecfbf5f,0x3f80be79,0x3d493f78,0x3d493f78,0xbf803e79,
0xbf71be16,0x3eacbf7d,0x3eacbf7d,0x3f713e16,0x3f3e3f04,0xbf2c3f5c,0xbf2c3f5c,0xbf3ebf04,0xbedbbf4e,0x3f67bf18,0x3f67bf18,0x3edb3f4e,
0xbdfb3f7c,0xbf7e3e2f,0xbf1dbf13,0x3f4abf51,0x3f27bf6a,0x3f423ecf,0x3d973f6f,0xbf7f3eb8,0xbf773f09,0xbe89bf58,0x3efcbf7a,0x3f5f3e60,
0x3f733cc9,0xbea13f80,0xbf653f31,0xbee6bf39,0xbf753dc9,0x3e95bf7f,0x3f75bdc9,0xbe953f7f,0x3ef13f22,0xbf623f46,0xbef1bf22,0x3f62bf46,
0x3e95bf7f,0x3f75bdc9,0xbe953f7f,0xbf753dc9,0xbf623f46,0xbef1bf22,0x3f62bf46,0x3ef13f22,0x3ee6bf80,0x3f65bcc9,0xbf733f39,0xbea1bf31,
0xbf7e3f13,0xbdfbbf51,0x3f4a3e2f,0xbf1d3f7c,0x3f273eb8,0xbf423f6f,0x3d97bf6a,0x3f7fbecf,0x3e89bf7a,0x3f77be60,0xbf5f3f58,0xbefcbf09,
0x3f4e3d49,0xbf183f80,0x3f18bf80,0x3f4e3d49,0x3e79bf71,0x3f78beac,0xbf783eac,0x3e79bf71,0xbf7d3f2c,0xbe16bf3e,0x3e163f3e,0xbf7d3f2c,
0x3f043edb,0xbf5c3f67,0x3f5cbf67,0x3f043edb,0xbf393f7e,0xbf31bdfb,0xbcc93f4a,0xbf803f1d,0x3f51bd97,0xbf133f7f,0x3f7cbf42,0x3e2f3f27,
0x3ecfbf77,0x3f6abe89,0xbeb8befc,0x3f6fbf5f,0xbf7a3ee6,0x3e60bf65,0xbf583f73,0xbf09bea1,0xbf0ebe48,0x3f55bf7b,0xbf0ebe48,0x3f55bf7b,
0xbf553f7b,0xbf0ebe48,0xbf553f7b,0xbf0ebe48,0x3f0e3e48,0xbf553f7b,0x3f0e3e48,0xbf553f7b,0x3f55bf7b,0x3f0e3e48,0x3f55bf7b,0x3f0e3e48,
0x3f6abf77,0x3ecf3e89,0x3f6fbefc,0xbeb83f5f,0xbe60bee6,0x3f7abf65,0x3f09bf73,0x3f58bea1,0xbf803f4a,0xbcc9bf1d,0xbf393dfb,0x3f31bf7e,
0xbe2f3f42,0xbf7c3f27,0xbf513f7f,0xbf13bd97,0x3e793eac,0xbf783f71,0xbf783f71,0xbe79beac,0x3f7dbf3e,0xbe163f2c,0xbe163f2c,0xbf7d3f3e,
0x3f04bf67,0x3f5cbedb,0x3f5cbedb,0xbf043f67,0xbf183d49,0x3f4ebf80,0x3f4ebf80,0x3f18bd49,0xbf7f3f6a,0xbd97becf,0x3f27bf6f,0x3f42beb8,
0xbefc3f58,0xbf5f3f09,0xbe89be60,0x3f77bf7a,0x3ee63cc9,0xbf653f80,0xbf733f31,0x3ea1bf39,0x3f7ebf51,0xbdfb3f13,0xbf4a3f7c,0xbf1d3e2f,
0x3dc9bef1,0x3f7fbf62,0xbdc93ef1,0xbf7f3f62,0xbf223e95,0x3f46bf75,0x3f22be95,0xbf463f75,0xbf7f3f62,0x3dc9bef1,0x3f7fbf62,0xbdc93ef1,
0xbf463f75,0xbf223e95,0x3f46bf75,0x3f22be95,0x3f77bf58,0xbe893f09,0xbefc3e60,0x3f5fbf7a,0x3f73bf80,0x3ea1bcc9,0xbf653f39,0x3ee6bf31,
0x3f1dbf51,0x3f4abf13,0xbf7e3f7c,0xbdfbbe2f,0x3d97beb8,0x3f7fbf6f,0xbf423f6a,0xbf273ecf,0xbedb3f18,0xbf673f4e,0x3f67bf4e,0xbedb3f18,
0xbd493e79,0xbf803f78,0x3f80bf78,0xbd493e79,0x3eacbe16,0xbf713f7d,0x3f71bf7d,0x3eacbe16,0x3f2cbf04,0xbf3e3f5c,0x3f3ebf5c,0x3f2cbf04,
0xbf513f42,0x3f13bf27,0xbf7c3f7f,0xbe2f3d97,0xbf6a3f5f,0x3ecfbefc,0xbf6f3f77,0xbeb83e89,0xbf7a3f73,0x3e60bea1,0xbf583f65,0xbf093ee6,
0xbf803f7e,0x3cc9bdfb,0xbf393f4a,0xbf313f1d,0x3f803f80,0xbf353f35,0x3f803f80,0xbf353f35,0x3f803f80,0xbf353f35,0x3f803f80,0xbf353f35,
0x3f803f80,0xbf353f35,0x3f803f80,0xbf353f35,0x3f803f80,0xbf353f35,0x3f803f80,0xbf353f35,0xbf7cbf7f,0x3e2f3d97,0xbf13bf27,0x3f513f42,
0xbf6fbf77,0x3eb83e89,0xbecfbefc,0x3f6a3f5f,0xbf58bf65,0x3f093ee6,0xbe60bea1,0x3f7a3f73,0xbf39bf4a,0x3f313f1d,0xbcc9bdfb,0x3f803f7e,
0x3f713f7d,0xbeacbe16,0xbeacbe16,0xbf71bf7d,0x3f3e3f5c,0xbf2cbf04,0xbf2cbf04,0xbf3ebf5c,0x3edb3f18,0xbf67bf4e,0xbf67bf4e,0xbedbbf18,
0x3d493e79,0xbf80bf78,0xbf80bf78,0xbd49be79,0xbf5fbf7a,0x3efc3e60,0x3f773f58,0x3e893f09,0xbee6bf31,0x3f653f39,0x3f733f80,0xbea1bcc9,
0x3dfbbe2f,0x3f7e3f7c,0x3f1d3f51,0xbf4abf13,0x3f273ecf,0x3f423f6a,0x3d973eb8,0xbf7fbf6f,0x3f463f75,0xbf22be95,0xbf46bf75,0x3f223e95,
0x3dc93ef1,0xbf7fbf62,0xbdc9bef1,0x3f7f3f62,0xbf22be95,0xbf46bf75,0x3f223e95,0x3f463f75,0xbf7fbf62,0xbdc9bef1,0x3f7f3f62,0x3dc93ef1,
0xbf27bf6f,0x3f423eb8,0xbd973ecf,0xbf7fbf6a,0x3e89be60,0x3f773f7a,0xbf5fbf09,0xbefcbf58,0x3f733f31,0x3ea13f39,0xbf65bf80,0x3ee6bcc9,
0x3f4a3f7c,0xbf1dbe2f,0xbdfbbf13,0x3f7e3f51,0x3f043f67,0xbf5cbedb,0x3f5c3edb,0x3f043f67,0xbf18bd49,0xbf4ebf80,0x3f4e3f80,0xbf18bd49,
0xbf78bf71,0x3e79beac,0xbe793eac,0xbf78bf71,0xbe16bf2c,0x3f7d3f3e,0xbf7dbf3e,0xbe16bf2c,0xbeb8bf5f,0x3f6f3efc,0xbf6abf77,0x3ecfbe89,
0x3f583ea1,0x3f093f73,0x3e60bee6,0x3f7a3f65,0x3f313f7e,0xbf39bdfb,0x3f803f4a,0xbcc93f1d,0xbf133d97,0xbf51bf7f,0x3e2f3f42,0xbf7cbf27,
0x3e483f55,0xbf7bbf0e,0x3e483f55,0xbf7bbf0e,0xbf7bbf0e,0xbe48bf55,0xbf7bbf0e,0xbe48bf55,0xbe48bf55,0x3f7b3f0e,0xbe48bf55,0x3f7b3f0e,
0x3f7b3f0e,0x3e483f55,0x3f7b3f0e,0x3e483f55,0xbcc9bf4a,0x3f803f1d,0x3f31bdfb,0x3f393f7e,0x3f7c3f42,0xbe2f3f27,0x3f133f7f,0xbf51bd97,
0xbeb83efc,0xbf6fbf5f,0xbf6abe89,0xbecfbf77,0xbf58bf73,0x3f09bea1,0xbe60bf65,0x3f7a3ee6,0xbe163f3e,0xbf7dbf2c,0xbf7dbf2c,0x3e16bf3e,
0xbf5cbf67,0x3f04bedb,0x3f04bedb,0x3f5c3f67,0x3f4ebd49,0x3f183f80,0x3f183f80,0xbf4e3d49,0x3e793f71,0xbf78beac,0xbf78beac,0xbe79bf71,
0x3ea1bf31,0x3f733f39,0x3ee63f80,0xbf65bcc9,0x3f1d3f7c,0xbf4a3e2f,0xbf7ebf13,0x3dfbbf51,0xbf7fbecf,0xbd97bf6a,0x3f27beb8,0x3f423f6f,
0x3efcbf09,0x3f5f3f58,0x3e893f7a,0xbf77be60,0xbef13f22,0xbf62bf46,0x3ef1bf22,0x3f623f46,0xbe95bf7f,0x3f753dc9,0x3e953f7f,0xbf75bdc9,
0x3f623f46,0xbef13f22,0xbf62bf46,0x3ef1bf22,0xbf75bdc9,0xbe95bf7f,0x3f753dc9,0x3e953f7f,0x3f1dbf13,0x3f4a3f51,0xbf7ebe2f,0xbdfbbf7c,
0xbd973f6f,0xbf7fbeb8,0x3f42becf,0x3f273f6a,0xbefcbf7a,0x3f5fbe60,0xbe893f58,0xbf77bf09,0x3f653f31,0xbee63f39,0xbea1bf80,0x3f73bcc9,
0xbf3e3f04,0xbf2cbf5c,0x3f2c3f5c,0xbf3e3f04,0x3edbbf4e,0x3f673f18,0xbf67bf18,0x3edbbf4e,0xbd493f78,0xbf80be79,0x3f803e79,0xbd493f78,
0xbeacbf7d,0x3f71be16,0xbf713e16,0xbeacbf7d,0x3f58bee6,0x3f093f65,0x3e60bf73,0x3f7a3ea1,0xbf393f1d,0xbf31bf4a,0xbcc93f7e,0xbf80bdfb,
0x3f13bf42,0x3f513f27,0xbe2fbf7f,0x3f7cbd97,0xbecf3f5f,0xbf6abefc,0x3eb83f77,0xbf6f3e89,0xbf6d3ec4,0xbec4bf6d,0xbf6d3ec4,0xbec4bf6d,
0x3f6dbec4,0x3ec43f6d,0x3f6dbec4,0x3ec43f6d,0xbf6d3ec4,0xbec4bf6d,0xbf6d3ec4,0xbec4bf6d,0x3f6dbec4,0x3ec43f6d,0x3f6dbec4,0x3ec43f6d,
0x3f7abea1,0x3e603f73,0x3f583ee6,0xbf093f65,0xbf803dfb,0xbcc9bf7e,0xbf39bf1d,0x3f31bf4a,0x3f7c3d97,0xbe2f3f7f,0x3f133f42,0xbf513f27,
0xbf6fbe89,0x3eb8bf77,0xbecfbf5f,0x3f6abefc,0xbf803e79,0xbd49bf78,0xbd49bf78,0x3f80be79,0x3f713e16,0xbeac3f7d,0xbeac3f7d,0xbf71be16,
0xbf3ebf04,0x3f2cbf5c,0x3f2cbf5c,0x3f3e3f04,0x3edb3f4e,0xbf673f18,0xbf673f18,0xbedbbf4e,0x3f7ebe2f,0xbdfb3f7c,0xbf4a3f51,0xbf1dbf13,
0xbf42becf,0x3f27bf6a,0x3f7fbeb8,0x3d973f6f,0x3e893f58,0xbf773f09,0xbf5fbe60,0x3efcbf7a,0x3ea1bf80,0x3f733cc9,0x3ee63f39,0xbf653f31,
0xbf753dc9,0x3e95bf7f,0x3f75bdc9,0xbe953f7f,0x3ef13f22,0xbf623f46,0xbef1bf22,0x3f62bf46,0x3e95bf7f,0x3f75bdc9,0xbe953f7f,0xbf753dc9,
0xbf623f46,0xbef1bf22,0x3f62bf46,0x3ef13f22,0x3f65bcc9,0xbee63f80,0xbea1bf31,0x3f73bf39,0xbdfbbf51,0x3f7ebf13,0xbf1d3f7c,0xbf4abe2f,
0xbf423f6f,0xbf27beb8,0x3f7fbecf,0xbd973f6a,0x3f77be60,0xbe893f7a,0xbefcbf09,0x3f5fbf58,0xbf4ebd49,0x3f18bf80,0xbf183f80,0xbf4ebd49,
0xbe793f71,0xbf783eac,0x3f78beac,0xbe793f71,0x3f7dbf2c,0x3e163f3e,0xbe16bf3e,0x3f7dbf2c,0xbf04bedb,0x3f5cbf67,0xbf5c3f67,0xbf04bedb,
0x3f313dfb,0xbf393f7e,0x3f80bf1d,0xbcc93f4a,0x3f13bf7f,0x3f51bd97,0xbe2fbf27,0x3f7cbf42,0xbf6a3e89,0x3ecfbf77,0xbf6f3f5f,0xbeb8befc,
0xbe603f65,0xbf7a3ee6,0x3f093ea1,0xbf583f73,0xbf0ebe48,0x3f55bf7b,0xbf0ebe48,0x3f55bf7b,0xbf553f7b,0xbf0ebe48,0xbf553f7b,0xbf0ebe48,
0x3f0e3e48,0xbf553f7b,0x3f0e3e48,0xbf553f7b,0x3f55bf7b,0x3f0e3e48,0x3f55bf7b,0x3f0e3e48,0x3ecf3e89,0xbf6a3f77,0xbeb83f5f,0xbf6f3efc,
0x3f7abf65,0x3e603ee6,0x3f58bea1,0xbf093f73,0xbcc9bf1d,0x3f80bf4a,0x3f31bf7e,0x3f39bdfb,0xbf7c3f27,0x3e2fbf42,0xbf13bd97,0x3f51bf7f,
0xbe79beac,0x3f78bf71,0x3f78bf71,0x3e793eac,0xbf7d3f3e,0x3e16bf2c,0x3e16bf2c,0x3f7dbf3e,0xbf043f67,0xbf5c3edb,0xbf5c3edb,0x3f04bf67,
0x3f18bd49,0xbf4e3f80,0xbf4e3f80,0xbf183d49,0x3d973ecf,0xbf7f3f6a,0xbf423eb8,0x3f27bf6f,0x3f5fbf09,0xbefc3f58,0xbf773f7a,0xbe89be60,
0x3f65bf80,0x3ee63cc9,0xbea13f39,0xbf733f31,0x3dfbbf13,0x3f7ebf51,0x3f1dbe2f,0xbf4a3f7c,0x3dc9bef1,0x3f7fbf62,0xbdc93ef1,0xbf7f3f62,
0xbf223e95,0x3f46bf75,0x3f22be95,0xbf463f75,0xbf7f3f62,0x3dc9bef1,0x3f7fbf62,0xbdc93ef1,0xbf463f75,0xbf223e95,0x3f46bf75,0x3f22be95,
0xbe893f09,0xbf773f58,0x3f5fbf7a,0x3efcbe60,0x3ea1bcc9,0xbf733f80,0x3ee6bf31,0x3f65bf39,0x3f4abf13,0xbf1d3f51,0xbdfbbe2f,0x3f7ebf7c,
0x3f7fbf6f,0xbd973eb8,0xbf273ecf,0x3f42bf6a,0x3edbbf18,0x3f67bf4e,0xbf673f4e,0x3edbbf18,0x3d49be79,0x3f80bf78,0xbf803f78,0x3d49be79,
0xbeac3e16,0x3f71bf7d,0xbf713f7d,0xbeac3e16,0xbf2c3f04,0x3f3ebf5c,0xbf3e3f5c,0xbf2c3f04,0xbf133f27,0xbf513f42,0x3e2fbd97,0xbf7c3f7f,
0xbecf3efc,0xbf6a3f5f,0x3eb8be89,0xbf6f3f77,0xbe603ea1,0xbf7a3f73,0x3f09bee6,0xbf583f65,0xbcc93dfb,0xbf803f7e,0x3f31bf1d,0xbf393f4a,
0x3f803f80,0xbf353f35,0x3f803f80,0xbf353f35,0x3f803f80,0xbf353f35,0x3f803f80,0xbf353f35,0x3f803f80,0xbf353f35,0x3f803f80,0xbf353f35,
0x3f803f80,0xbf353f35,0x3f803f80,0xbf353f35,0x3e2f3d97,0x3f7c3f7f,0x3f513f42,0x3f133f27,0x3eb83e89,0x3f6f3f77,0x3f6a3f5f,0x3ecf3efc,
0x3f093ee6,0x3f583f65,0x3f7a3f73,0x3e603ea1,0x3f313f1d,0x3f393f4a,0x3f803f7e,0x3cc93dfb,0xbf71bf7d,0x3eac3e16,0x3eac3e16,0x3f713f7d,
0xbf3ebf5c,0x3f2c3f04,0x3f2c3f04,0x3f3e3f5c,0xbedbbf18,0x3f673f4e,0x3f673f4e,0x3edb3f18,0xbd49be79,0x3f803f78,0x3f803f78,0x3d493e79,
0xbefcbe60,0xbf5fbf7a,0xbe89bf09,0x3f773f58,0xbf65bf39,0xbee6bf31,0x3ea13cc9,0x3f733f80,0xbf7ebf7c,0x3dfbbe2f,0x3f4a3f13,0x3f1d3f51,
0xbf42bf6a,0x3f273ecf,0x3f7f3f6f,0x3d973eb8,0x3f463f75,0xbf22be95,0xbf46bf75,0x3f223e95,0x3dc93ef1,0xbf7fbf62,0xbdc9bef1,0x3f7f3f62,
0xbf22be95,0xbf46bf75,0x3f223e95,0x3f463f75,0xbf7fbf62,0xbdc9bef1,0x3f7f3f62,0x3dc93ef1,0x3f423eb8,0x3f273f6f,0xbf7fbf6a,0x3d97becf,
0x3f773f7a,0xbe893e60,0xbefcbf58,0x3f5f3f09,0x3ea13f39,0xbf73bf31,0x3ee6bcc9,0x3f653f80,0xbf1dbe2f,0xbf4abf7c,0x3f7e3f51,0x3dfb3f13,
0xbf04bf67,0x3f5c3edb,0xbf5cbedb,0xbf04bf67,0x3f183d49,0x3f4e3f80,0xbf4ebf80,0x3f183d49,0x3f783f71,0xbe793eac,0x3e79beac,0x3f783f71,
0x3e163f2c,0xbf7dbf3e,0x3f7d3f3e,0x3e163f2c,0xbf6fbefc,0xbeb8bf5f,0xbecf3e89,0xbf6abf77,0xbf09bf73,0x3f583ea1,0xbf7abf65,0x3e60bee6,
0x3f393dfb,0x3f313f7e,0x3cc9bf1d,0x3f803f4a,0x3f513f7f,0xbf133d97,0x3f7c3f27,0x3e2f3f42,0x3e483f55,0xbf7bbf0e,0x3e483f55,0xbf7bbf0e,
0xbf7bbf0e,0xbe48bf55,0xbf7bbf0e,0xbe48bf55,0xbe48bf55,0x3f7b3f0e,0xbe48bf55,0x3f7b3f0e,0x3f7b3f0e,0x3e483f55,0x3f7b3f0e,0x3e483f55,
0x3f803f1d,0x3cc93f4a,0x3f393f7e,0xbf313dfb,0xbe2f3f27,0xbf7cbf42,0xbf51bd97,0xbf13bf7f,0xbf6fbf5f,0x3eb8befc,0xbecfbf77,0x3f6a3e89,
0x3f09bea1,0x3f583f73,0x3f7a3ee6,0x3e603f65,0x3e16bf3e,0x3f7d3f2c,0x3f7d3f2c,0xbe163f3e,0x3f5c3f67,0xbf043edb,0xbf043edb,0xbf5cbf67,
0xbf4e3d49,0xbf18bf80,0xbf18bf80,0x3f4ebd49,0xbe79bf71,0x3f783eac,0x3f783eac,0x3e793f71,0xbf73bf39,0x3ea1bf31,0x3f653cc9,0x3ee63f80,
0x3f4abe2f,0x3f1d3f7c,0xbdfb3f51,0xbf7ebf13,0x3d973f6a,0xbf7fbecf,0xbf42bf6f,0x3f27beb8,0xbf5fbf58,0x3efcbf09,0x3f773e60,0x3e893f7a,
0xbef13f22,0xbf62bf46,0x3ef1bf22,0x3f623f46,0xbe95bf7f,0x3f753dc9,0x3e953f7f,0xbf75bdc9,0x3f623f46,0xbef13f22,0xbf62bf46,0x3ef1bf22,
0xbf75bdc9,0xbe95bf7f,0x3f753dc9,0x3e953f7f,0x3f4a3f51,0xbf1d3f13,0xbdfbbf7c,0x3f7e3e2f,0xbf7fbeb8,0x3d97bf6f,0x3f273f6a,0xbf423ecf,
0x3f5fbe60,0x3efc3f7a,0xbf77bf09,0x3e89bf58,0xbee63f39,0xbf65bf31,0x3f73bcc9,0x3ea13f80,0x3f3ebf04,0x3f2c3f5c,0xbf2cbf5c,0x3f3ebf04,
0xbedb3f4e,0xbf67bf18,0x3f673f18,0xbedb3f4e,0x3d49bf78,0x3f803e79,0xbf80be79,0x3d49bf78,0x3eac3f7d,0xbf713e16,0x3f71be16,0x3eac3f7d,
0xbf09bf65,0x3f58bee6,0xbf7abea1,0x3e60bf73,0x3f313f4a,0xbf393f1d,0x3f803dfb,0xbcc93f7e,0xbf51bf27,0x3f13bf42,0xbf7c3d97,0xbe2fbf7f,
0x3f6a3efc,0xbecf3f5f,0x3f6fbe89,0x3eb83f77,0xbf6d3ec4,0xbec4bf6d,0xbf6d3ec4,0xbec4bf6d,0x3f6dbec4,0x3ec43f6d,0x3f6dbec4,0x3ec43f6d,
0xbf6d3ec4,0xbec4bf6d,0xbf6d3ec4,0xbec4bf6d,0x3f6dbec4,0x3ec43f6d,0x3f6dbec4,0x3ec43f6d,0x3e603f73,0xbf7a3ea1,0xbf093f65,0xbf58bee6,
0xbcc9bf7e,0x3f80bdfb,0x3f31bf4a,0x3f393f1d,0xbe2f3f7f,0xbf7cbd97,0xbf513f27,0xbf13bf42,0x3eb8bf77,0x3f6f3e89,0x3f6abefc,0x3ecf3f5f,
0x3f80be79,0x3d493f78,0x3d493f78,0xbf803e79,0xbf71be16,0x3eacbf7d,0x3eacbf7d,0x3f713e16,0x3f3e3f04,0xbf2c3f5c,0xbf2c3f5c,0xbf3ebf04,
0xbedbbf4e,0x3f67bf18,0x3f67bf18,0x3edb3f4e,0x3dfbbf7c,0x3f7ebe2f,0x3f1d3f13,0xbf4a3f51,0xbf273f6a,0xbf42becf,0xbd97bf6f,0x3f7fbeb8,
0x3f77bf09,0x3e893f58,0xbefc3f7a,0xbf5fbe60,0xbf73bcc9,0x3ea1bf80,0x3f65bf31,0x3ee63f39,0xbf753dc9,0x3e95bf7f,0x3f75bdc9,0xbe953f7f,
0x3ef13f22,0xbf623f46,0xbef1bf22,0x3f62bf46,0x3e95bf7f,0x3f75bdc9,0xbe953f7f,0xbf753dc9,0xbf623f46,0xbef1bf22,0x3f62bf46,0x3ef13f22,
0xbee63f80,0xbf653cc9,0x3f73bf39,0x3ea13f31,0x3f7ebf13,0x3dfb3f51,0xbf4abe2f,0x3f1dbf7c,0xbf27beb8,0x3f42bf6f,0xbd973f6a,0xbf7f3ecf,
0xbe893f7a,0xbf773e60,0x3f5fbf58,0x3efc3f09,0x3f4e3d49,0xbf183f80,0x3f18bf80,0x3f4e3d49,0x3e79bf71,0x3f78beac,0xbf783eac,0x3e79bf71,
0xbf7d3f2c,0xbe16bf3e,0x3e163f3e,0xbf7d3f2c,0x3f043edb,0xbf5c3f67,0x3f5cbf67,0x3f043edb,0x3f39bf7e,0x3f313dfb,0x3cc9bf4a,0x3f80bf1d,
0xbf513d97,0x3f13bf7f,0xbf7c3f42,0xbe2fbf27,0xbecf3f77,0xbf6a3e89,0x3eb83efc,0xbf6f3f5f,0x3f7abee6,0xbe603f65,0x3f58bf73,0x3f093ea1,
0xbf0ebe48,0x3f55bf7b,0xbf0ebe48,0x3f55bf7b,0xbf553f7b,0xbf0ebe48,0xbf553f7b,0xbf0ebe48,0x3f0e3e48,0xbf553f7b,0x3f0e3e48,0xbf553f7b,
0x3f55bf7b,0x3f0e3e48,0x3f55bf7b,0x3f0e3e48,0xbf6a3f77,0xbecfbe89,0xbf6f3efc,0x3eb8bf5f,0x3e603ee6,0xbf7a3f65,0xbf093f73,0xbf583ea1,
0x3f80bf4a,0x3cc93f1d,0x3f39bdfb,0xbf313f7e,0x3e2fbf42,0x3f7cbf27,0x3f51bf7f,0x3f133d97,0x3e793eac,0xbf783f71,0xbf783f71,0xbe79beac,
0x3f7dbf3e,0xbe163f2c,0xbe163f2c,0xbf7d3f3e,0x3f04bf67,0x3f5cbedb,0x3f5cbedb,0xbf043f67,0xbf183d49,0x3f4ebf80,0x3f4ebf80,0x3f18bd49,
0x3f7fbf6a,0x3d973ecf,0xbf273f6f,0xbf423eb8,0x3efcbf58,0x3f5fbf09,0x3e893e60,0xbf773f7a,0xbee6bcc9,0x3f65bf80,0x3f73bf31,0xbea13f39,
0xbf7e3f51,0x3dfbbf13,0x3f4abf7c,0x3f1dbe2f,0x3dc9bef1,0x3f7fbf62,0xbdc93ef1,0xbf7f3f62,0xbf223e95,0x3f46bf75,0x3f22be95,0xbf463f75,
0xbf7f3f62,0x3dc9bef1,0x3f7fbf62,0xbdc93ef1,0xbf463f75,0xbf223e95,0x3f46bf75,0x3f22be95,0xbf773f58,0x3e89bf09,0x3efcbe60,0xbf5f3f7a,
0xbf733f80,0xbea13cc9,0x3f65bf39,0xbee63f31,0xbf1d3f51,0xbf4a3f13,0x3f7ebf7c,0x3dfb3e2f,0xbd973eb8,0xbf7f3f6f,0x3f42bf6a,0x3f27becf,
0xbedb3f18,0xbf673f4e,0x3f67bf4e,0xbedb3f18,0xbd493e79,0xbf803f78,0x3f80bf78,0xbd493e79,0x3eacbe16,0xbf713f7d,0x3f71bf7d,0x3eacbe16,
0x3f2cbf04,0xbf3e3f5c,0x3f3ebf5c,0x3f2cbf04,0x3f51bf42,0xbf133f27,0x3f7cbf7f,0x3e2fbd97,0x3f6abf5f,0xbecf3efc,0x3f6fbf77,0x3eb8be89,
0x3f7abf73,0xbe603ea1,0x3f58bf65,0x3f09bee6,0x3f80bf7e,0xbcc93dfb,0x3f39bf4a,0x3f31bf1d,0x3f803f80,0x3f803f80,0x3f803f80,0x3f803f80,
0x0,0x0,0x0,0x0,0x3f803f80,0x3f803f80,0x3f803f80,0x3f803f80,0x0,0x0,0x0,0x0,
0x3f803f80,0x3f803f80,0x3f803f80,0x3f803f80,0x0,0x0,0x0,0x0,0x3f803f80,0x3f803f80,0x3f803f80,0x3f803f80,
0x0,0x0,0x0,0x0,0x3e480000,0x3f0e3ec4,0x3f553f35,0x3f7b3f6d,0x3f7b3f80,0x3f553f6d,0x3f0e3f35,0x3e483ec4,
0x3f7b3f80,0x3f553f6d,0x3f0e3f35,0x3e483ec4,0xbe480000,0xbf0ebec4,0xbf55bf35,0xbf7bbf6d,0xbe480000,0xbf0ebec4,0xbf55bf35,0xbf7bbf6d,
0xbf7bbf80,0xbf55bf6d,0xbf0ebf35,0xbe48bec4,0xbf7bbf80,0xbf55bf6d,0xbf0ebf35,0xbe48bec4,0x3e480000,0x3f0e3ec4,0x3f553f35,0x3f7b3f6d,
0xbf6dbf80,0xbec4bf35,0x3ec40000,0x3f6d3f35,0xbec40000,0xbf6dbf35,0xbf6dbf80,0xbec4bf35,0x3f6d3f80,0x3ec43f35,0xbec40000,0xbf6dbf35,
0x3ec40000,0x3f6d3f35,0x3f6d3f80,0x3ec43f35,0xbf6dbf80,0xbec4bf35,0x3ec40000,0x3f6d3f35,0xbec40000,0xbf6dbf35,0xbf6dbf80,0xbec4bf35,
0x3f6d3f80,0x3ec43f35,0xbec40000,0xbf6dbf35,0x3ec40000,0x3f6d3f35,0x3f6d3f80,0x3ec43f35,0xbf55bf80,0x3e48bec4,0x3f7b3f35,0x3f0e3f6d,
0x3f0e0000,0x3f7b3f6d,0x3e483f35,0xbf55bec4,0x3f0e0000,0x3f7b3f6d,0x3e483f35,0xbf55bec4,0x3f553f80,0xbe483ec4,0xbf7bbf35,0xbf0ebf6d,
0x3f553f80,0xbe483ec4,0xbf7bbf35,0xbf0ebf6d,0xbf0e0000,0xbf7bbf6d,0xbe48bf35,0x3f553ec4,0xbf0e0000,0xbf7bbf6d,0xbe48bf35,0x3f553ec4,
0xbf55bf80,0x3e48bec4,0x3f7b3f35,0x3f0e3f6d,0x3f353f80,0xbf350000,0xbf35bf80,0x3f350000,0x3f350000,0x3f353f80,0xbf350000,0xbf35bf80,
0x3f353f80,0xbf350000,0xbf35bf80,0x3f350000,0x3f350000,0x3f353f80,0xbf350000,0xbf35bf80,0x3f353f80,0xbf350000,0xbf35bf80,0x3f350000,
0x3f350000,0x3f353f80,0xbf350000,0xbf35bf80,0x3f353f80,0xbf350000,0xbf35bf80,0x3f350000,0x3f350000,0x3f353f80,0xbf350000,0xbf35bf80,
0xbf550000,0xbe48bf6d,0x3f7b3f35,0xbf0e3ec4,0xbf0ebf80,0x3f7b3ec4,0xbe483f35,0xbf55bf6d,0xbf0ebf80,0x3f7b3ec4,0xbe483f35,0xbf55bf6d,
0x3f550000,0x3e483f6d,0xbf7bbf35,0x3f0ebec4,0x3f550000,0x3e483f6d,0xbf7bbf35,0x3f0ebec4,0x3f0e3f80,0xbf7bbec4,0x3e48bf35,0x3f553f6d,
0x3f0e3f80,0xbf7bbec4,0x3e48bf35,0x3f553f6d,0xbf550000,0xbe48bf6d,0x3f7b3f35,0xbf0e3ec4,0xbec4bf80,0x3f6d3f35,0xbf6d0000,0x3ec4bf35,
0xbf6d0000,0x3ec4bf35,0x3ec43f80,0xbf6dbf35,0x3ec43f80,0xbf6dbf35,0x3f6d0000,0xbec43f35,0x3f6d0000,0xbec43f35,0xbec4bf80,0x3f6d3f35,
0xbec4bf80,0x3f6d3f35,0xbf6d0000,0x3ec4bf35,0xbf6d0000,0x3ec4bf35,0x3ec43f80,0xbf6dbf35,0x3ec43f80,0xbf6dbf35,0x3f6d0000,0xbec43f35,
0x3f6d0000,0xbec43f35,0xbec4bf80,0x3f6d3f35,0x3e483f80,0xbf0ebf6d,0x3f553f35,0xbf7bbec4,0xbf7b0000,0x3f55bec4,0xbf0e3f35,0x3e48bf6d,
0xbf7b0000,0x3f55bec4,0xbf0e3f35,0x3e48bf6d,0xbe48bf80,0x3f0e3f6d,0xbf55bf35,0x3f7b3ec4,0xbe48bf80,0x3f0e3f6d,0xbf55bf35,0x3f7b3ec4,
0x3f7b0000,0xbf553ec4,0x3f0ebf35,0xbe483f6d,0x3f7b0000,0xbf553ec4,0x3f0ebf35,0xbe483f6d,0x3e483f80,0xbf0ebf6d,0x3f553f35,0xbf7bbec4,
0x80008000,0x80008000,0x80008000,0x80008000,0x3f803f80,0x3f803f80,0x3f803f80,0x3f803f80,0x80008000,0x80008000,0x80008000,0x80008000,
0x3f803f80,0x3f803f80,0x3f803f80,0x3f803f80,0x80008000,0x80008000,0x80008000,0x80008000,0x3f803f80,0x3f803f80,0x3f803f80,0x3f803f80,
0x80008000,0x80008000,0x80008000,0x80008000,0x3f803f80,0x3f803f80,0x3f803f80,0x3f803f80,0x3f7b3f80,0x3f553f6d,0x3f0e3f35,0x3e483ec4,
0xbe488000,0xbf0ebec4,0xbf55bf35,0xbf7bbf6d,0xbe480000,0xbf0ebec4,0xbf55bf35,0xbf7bbf6d,0xbf7bbf80,0xbf55bf6d,0xbf0ebf35,0xbe48bec4,
0xbf7bbf80,0xbf55bf6d,0xbf0ebf35,0xbe48bec4,0x3e488000,0x3f0e3ec4,0x3f553f35,0x3f7b3f6d,0x3e480000,0x3f0e3ec4,0x3f553f35,0x3f7b3f6d,
0x3f7b3f80,0x3f553f6d,0x3f0e3f35,0x3e483ec4,0x3ec48000,0x3f6d3f35,0x3f6d3f80,0x3ec43f35,0xbf6dbf80,0xbec4bf35,0x3ec40000,0x3f6d3f35,
0xbec48000,0xbf6dbf35,0xbf6dbf80,0xbec4bf35,0x3f6d3f80,0x3ec43f35,0xbec40000,0xbf6dbf35,0x3ec48000,0x3f6d3f35,0x3f6d3f80,0x3ec43f35,
0xbf6dbf80,0xbec4bf35,0x3ec40000,0x3f6d3f35,0xbec48000,0xbf6dbf35,0xbf6dbf80,0xbec4bf35,0x3f6d3f80,0x3ec43f35,0xbec40000,0xbf6dbf35,
0x3f0e0000,0x3f7b3f6d,0x3e483f35,0xbf55bec4,0x3f553f80,0xbe483ec4,0xbf7bbf35,0xbf0ebf6d,0x3f553f80,0xbe483ec4,0xbf7bbf35,0xbf0ebf6d,
0xbf0e8000,0xbf7bbf6d,0xbe48bf35,0x3f553ec4,0xbf0e0000,0xbf7bbf6d,0xbe48bf35,0x3f553ec4,0xbf55bf80,0x3e48bec4,0x3f7b3f35,0x3f0e3f6d,
0xbf55bf80,0x3e48bec4,0x3f7b3f35,0x3f0e3f6d,0x3f0e8000,0x3f7b3f6d,0x3e483f35,0xbf55bec4,0xbf358000,0xbf35bf80,0x3f358000,0x3f353f80,
0x3f353f80,0xbf350000,0xbf35bf80,0x3f350000,0xbf358000,0xbf35bf80,0x3f358000,0x3f353f80,0x3f353f80,0xbf350000,0xbf35bf80,0x3f350000,
0xbf358000,0xbf35bf80,0x3f358000,0x3f353f80,0x3f353f80,0xbf350000,0xbf35bf80,0x3f350000,0xbf358000,0xbf35bf80,0x3f358000,0x3f353f80,
0x3f353f80,0xbf350000,0xbf35bf80,0x3f350000,0xbf0ebf80,0x3f7b3ec4,0xbe483f35,0xbf55bf6d,0x3f558000,0x3e483f6d,0xbf7bbf35,0x3f0ebec4,
0x3f550000,0x3e483f6d,0xbf7bbf35,0x3f0ebec4,0x3f0e3f80,0xbf7bbec4,0x3e48bf35,0x3f553f6d,0x3f0e3f80,0xbf7bbec4,0x3e48bf35,0x3f553f6d,
0xbf558000,0xbe48bf6d,0x3f7b3f35,0xbf0e3ec4,0xbf550000,0xbe48bf6d,0x3f7b3f35,0xbf0e3ec4,0xbf0ebf80,0x3f7b3ec4,0xbe483f35,0xbf55bf6d,
0x3f6d8000,0xbec43f35,0xbec4bf80,0x3f6d3f35,0xbec4bf80,0x3f6d3f35,0xbf6d0000,0x3ec4bf35,0xbf6d8000,0x3ec4bf35,0x3ec43f80,0xbf6dbf35,
0x3ec43f80,0xbf6dbf35,0x3f6d0000,0xbec43f35,0x3f6d8000,0xbec43f35,0xbec4bf80,0x3f6d3f35,0xbec4bf80,0x3f6d3f35,0xbf6d0000,0x3ec4bf35,
0xbf6d8000,0x3ec4bf35,0x3ec43f80,0xbf6dbf35,0x3ec43f80,0xbf6dbf35,0x3f6d0000,0xbec43f35,0xbf7b0000,0x3f55bec4,0xbf0e3f35,0x3e48bf6d,
0xbe48bf80,0x3f0e3f6d,0xbf55bf35,0x3f7b3ec4,0xbe48bf80,0x3f0e3f6d,0xbf55bf35,0x3f7b3ec4,0x3f7b8000,0xbf553ec4,0x3f0ebf35,0xbe483f6d,
0x3f7b0000,0xbf553ec4,0x3f0ebf35,0xbe483f6d,0x3e483f80,0xbf0ebf6d,0x3f553f35,0xbf7bbec4,0x3e483f80,0xbf0ebf6d,0x3f553f35,0xbf7bbec4,
0xbf7b8000,0x3f55bec4,0xbf0e3f35,0x3e48bf6d,0x3f80,0xbf80,0x3f80,0xbf80,0x3f800000,0xbf800000,0x3f800000,0xbf800000,
0x3f80,0xbf80,0x3f80,0xbf80,0x3f800000,0xbf800000,0x3f800000,0xbf800000,0x3f80,0xbf80,0x3f80,0xbf80,
0x3f800000,0xbf800000,0x3f800000,0xbf800000,0x3f80,0xbf80,0x3f80,0xbf80,0x3f800000,0xbf800000,0x3f800000,0xbf800000,
0x3f7b0000,0xbf55bec4,0x3f0e3f35,0xbe48bf6d,0xbe483f80,0x3f0ebf6d,0xbf553f35,0x3f7bbec4,0xbe483f80,0x3f0ebf6d,0xbf553f35,0x3f7bbec4,
0xbf7b0000,0x3f553ec4,0xbf0ebf35,0x3e483f6d,0xbf7b0000,0x3f553ec4,0xbf0ebf35,0x3e483f6d,0x3e48bf80,0xbf0e3f6d,0x3f55bf35,0xbf7b3ec4,
0x3e48bf80,0xbf0e3f6d,0x3f55bf35,0xbf7b3ec4,0x3f7b0000,0xbf55bec4,0x3f0e3f35,0xbe48bf6d,0x3ec4bf80,0xbf6d3f35,0x3f6d0000,0xbec4bf35,
0xbf6d0000,0x3ec43f35,0x3ec4bf80,0xbf6d3f35,0xbec43f80,0x3f6dbf35,0xbf6d0000,0x3ec43f35,0x3f6d0000,0xbec4bf35,0xbec43f80,0x3f6dbf35,
0x3ec4bf80,0xbf6d3f35,0x3f6d0000,0xbec4bf35,0xbf6d0000,0x3ec43f35,0x3ec4bf80,0xbf6d3f35,0xbec43f80,0x3f6dbf35,0xbf6d0000,0x3ec43f35,
0x3f6d0000,0xbec4bf35,0xbec43f80,0x3f6dbf35,0x3f0ebf80,0xbf7b3ec4,0x3e483f35,0x3f55bf6d,0x3f550000,0x3e48bf6d,0xbf7b3f35,0x3f0e3ec4,
0x3f550000,0x3e48bf6d,0xbf7b3f35,0x3f0e3ec4,0xbf0e3f80,0x3f7bbec4,0xbe48bf35,0xbf553f6d,0xbf0e3f80,0x3f7bbec4,0xbe48bf35,0xbf553f6d,
0xbf550000,0xbe483f6d,0x3f7bbf35,0xbf0ebec4,0xbf550000,0xbe483f6d,0x3f7bbf35,0xbf0ebec4,0x3f0ebf80,0xbf7b3ec4,0x3e483f35,0x3f55bf6d,
0xbf353f80,0x3f350000,0x3f35bf80,0xbf350000,0x3f350000,0x3f35bf80,0xbf350000,0xbf353f80,0xbf353f80,0x3f350000,0x3f35bf80,0xbf350000,
0x3f350000,0x3f35bf80,0xbf350000,0xbf353f80,0xbf353f80,0x3f350000,0x3f35bf80,0xbf350000,0x3f350000,0x3f35bf80,0xbf350000,0xbf353f80,
0xbf353f80,0x3f350000,0x3f35bf80,0xbf350000,0x3f350000,0x3f35bf80,0xbf350000,0xbf353f80,0xbf0e0000,0xbf7b3f6d,0xbe483f35,0x3f55bec4,
0x3f55bf80,0xbe48bec4,0xbf7b3f35,0xbf0e3f6d,0x3f55bf80,0xbe48bec4,0xbf7b3f35,0xbf0e3f6d,0x3f0e0000,0x3f7bbf6d,0x3e48bf35,0xbf553ec4,
0x3f0e0000,0x3f7bbf6d,0x3e48bf35,0xbf553ec4,0xbf553f80,0x3e483ec4,0x3f7bbf35,0x3f0ebf6d,0xbf553f80,0x3e483ec4,0x3f7bbf35,0x3f0ebf6d,
0xbf0e0000,0xbf7b3f6d,0xbe483f35,0x3f55bec4,0x3f6dbf80,0x3ec4bf35,0xbec40000,0xbf6d3f35,0xbec40000,0xbf6d3f35,0xbf6d3f80,0xbec43f35,
0xbf6d3f80,0xbec43f35,0x3ec40000,0x3f6dbf35,0x3ec40000,0x3f6dbf35,0x3f6dbf80,0x3ec4bf35,0x3f6dbf80,0x3ec4bf35,0xbec40000,0xbf6d3f35,
0xbec40000,0xbf6d3f35,0xbf6d3f80,0xbec43f35,0xbf6d3f80,0xbec43f35,0x3ec40000,0x3f6dbf35,0x3ec40000,0x3f6dbf35,0x3f6dbf80,0x3ec4bf35,
0xbf7b3f80,0xbf553f6d,0xbf0e3f35,0xbe483ec4,0xbe480000,0xbf0e3ec4,0xbf553f35,0xbf7b3f6d,0xbe480000,0xbf0e3ec4,0xbf553f35,0xbf7b3f6d,
0x3f7bbf80,0x3f55bf6d,0x3f0ebf35,0x3e48bec4,0x3f7bbf80,0x3f55bf6d,0x3f0ebf35,0x3e48bec4,0x3e480000,0x3f0ebec4,0x3f55bf35,0x3f7bbf6d,
0x3e480000,0x3f0ebec4,0x3f55bf35,0x3f7bbf6d,0xbf7b3f80,0xbf553f6d,0xbf0e3f35,0xbe483ec4,0xbf808000,0x3f808000,0xbf808000,0x3f808000,
0x3f80,0xbf80,0x3f80,0xbf80,0xbf808000,0x3f808000,0xbf808000,0x3f808000,0x3f80,0xbf80,0x3f80,0xbf80,
0xbf808000,0x3f808000,0xbf808000,0x3f808000,0x3f80,0xbf80,0x3f80,0xbf80,0xbf808000,0x3f808000,0xbf808000,0x3f808000,
0x3f80,0xbf80,0x3f80,0xbf80,0xbe483f80,0x3f0ebf6d,0xbf553f35,0x3f7bbec4,0xbf7b8000,0x3f553ec4,0xbf0ebf35,0x3e483f6d,
0xbf7b0000,0x3f553ec4,0xbf0ebf35,0x3e483f6d,0x3e48bf80,0xbf0e3f6d,0x3f55bf35,0xbf7b3ec4,0x3e48bf80,0xbf0e3f6d,0x3f55bf35,0xbf7b3ec4,
0x3f7b8000,0xbf55bec4,0x3f0e3f35,0xbe48bf6d,0x3f7b0000,0xbf55bec4,0x3f0e3f35,0xbe48bf6d,0xbe483f80,0x3f0ebf6d,0xbf553f35,0x3f7bbec4,
0x3f6d8000,0xbec4bf35,0xbec43f80,0x3f6dbf35,0x3ec4bf80,0xbf6d3f35,0x3f6d0000,0xbec4bf35,0xbf6d8000,0x3ec43f35,0x3ec4bf80,0xbf6d3f35,
0xbec43f80,0x3f6dbf35,0xbf6d0000,0x3ec43f35,0x3f6d8000,0xbec4bf35,0xbec43f80,0x3f6dbf35,0x3ec4bf80,0xbf6d3f35,0x3f6d0000,0xbec4bf35,
0xbf6d8000,0x3ec43f35,0x3ec4bf80,0xbf6d3f35,0xbec43f80,0x3f6dbf35,0xbf6d0000,0x3ec43f35,0x3f550000,0x3e48bf6d,0xbf7b3f35,0x3f0e3ec4,
0xbf0e3f80,0x3f7bbec4,0xbe48bf35,0xbf553f6d,0xbf0e3f80,0x3f7bbec4,0xbe48bf35,0xbf553f6d,0xbf558000,0xbe483f6d,0x3f7bbf35,0xbf0ebec4,
0xbf550000,0xbe483f6d,0x3f7bbf35,0xbf0ebec4,0x3f0ebf80,0xbf7b3ec4,0x3e483f35,0x3f55bf6d,0x3f0ebf80,0xbf7b3ec4,0x3e483f35,0x3f55bf6d,
0x3f558000,0x3e48bf6d,0xbf7b3f35,0x3f0e3ec4,0xbf358000,0xbf353f80,0x3f358000,0x3f35bf80,0xbf353f80,0x3f350000,0x3f35bf80,0xbf350000,
0xbf358000,0xbf353f80,0x3f358000,0x3f35bf80,0xbf353f80,0x3f350000,0x3f35bf80,0xbf350000,0xbf358000,0xbf353f80,0x3f358000,0x3f35bf80,
0xbf353f80,0x3f350000,0x3f35bf80,0xbf350000,0xbf358000,0xbf353f80,0x3f358000,0x3f35bf80,0xbf353f80,0x3f350000,0x3f35bf80,0xbf350000,
0x3f55bf80,0xbe48bec4,0xbf7b3f35,0xbf0e3f6d,0x3f0e8000,0x3f7bbf6d,0x3e48bf35,0xbf553ec4,0x3f0e0000,0x3f7bbf6d,0x3e48bf35,0xbf553ec4,
0xbf553f80,0x3e483ec4,0x3f7bbf35,0x3f0ebf6d,0xbf553f80,0x3e483ec4,0x3f7bbf35,0x3f0ebf6d,0xbf0e8000,0xbf7b3f6d,0xbe483f35,0x3f55bec4,
0xbf0e0000,0xbf7b3f6d,0xbe483f35,0x3f55bec4,0x3f55bf80,0xbe48bec4,0xbf7b3f35,0xbf0e3f6d,0x3ec48000,0x3f6dbf35,0x3f6dbf80,0x3ec4bf35,
0x3f6dbf80,0x3ec4bf35,0xbec40000,0xbf6d3f35,0xbec48000,0xbf6d3f35,0xbf6d3f80,0xbec43f35,0xbf6d3f80,0xbec43f35,0x3ec40000,0x3f6dbf35,
0x3ec48000,0x3f6dbf35,0x3f6dbf80,0x3ec4bf35,0x3f6dbf80,0x3ec4bf35,0xbec40000,0xbf6d3f35,0xbec48000,0xbf6d3f35,0xbf6d3f80,0xbec43f35,
0xbf6d3f80,0xbec43f35,0x3ec40000,0x3f6dbf35,0xbe480000,0xbf0e3ec4,0xbf553f35,0xbf7b3f6d,0x3f7bbf80,0x3f55bf6d,0x3f0ebf35,0x3e48bec4,
0x3f7bbf80,0x3f55bf6d,0x3f0ebf35,0x3e48bec4,0x3e488000,0x3f0ebec4,0x3f55bf35,0x3f7bbf6d,0x3e480000,0x3f0ebec4,0x3f55bf35,0x3f7bbf6d,
0xbf7b3f80,0xbf553f6d,0xbf0e3f35,0xbe483ec4,0xbf7b3f80,0xbf553f6d,0xbf0e3f35,0xbe483ec4,0xbe488000,0xbf0e3ec4,0xbf553f35,0xbf7b3f6d,
0xbf803f80,0xbf803f80,0xbf803f80,0xbf803f80,0x0,0x0,0x0,0x0,0xbf803f80,0xbf803f80,0xbf803f80,0xbf803f80,
0x0,0x0,0x0,0x0,0xbf803f80,0xbf803f80,0xbf803f80,0xbf803f80,0x0,0x0,0x0,0x0,
0xbf803f80,0xbf803f80,0xbf803f80,0xbf803f80,0x0,0x0,0x0,0x0,0xbe480000,0xbf0e3ec4,0xbf553f35,0xbf7b3f6d,
0xbf7b3f80,0xbf553f6d,0xbf0e3f35,0xbe483ec4,0xbf7b3f80,0xbf553f6d,0xbf0e3f35,0xbe483ec4,0x3e480000,0x3f0ebec4,0x3f55bf35,0x3f7bbf6d,
0x3e480000,0x3f0ebec4,0x3f55bf35,0x3f7bbf6d,0x3f7bbf80,0x3f55bf6d,0x3f0ebf35,0x3e48bec4,0x3f7bbf80,0x3f55bf6d,0x3f0ebf35,0x3e48bec4,
0xbe480000,0xbf0e3ec4,0xbf553f35,0xbf7b3f6d,0x3f6dbf80,0x3ec4bf35,0xbec40000,0xbf6d3f35,0x3ec40000,0x3f6dbf35,0x3f6dbf80,0x3ec4bf35,
0xbf6d3f80,0xbec43f35,0x3ec40000,0x3f6dbf35,0xbec40000,0xbf6d3f35,0xbf6d3f80,0xbec43f35,0x3f6dbf80,0x3ec4bf35,0xbec40000,0xbf6d3f35,
0x3ec40000,0x3f6dbf35,0x3f6dbf80,0x3ec4bf35,0xbf6d3f80,0xbec43f35,0x3ec40000,0x3f6dbf35,0xbec40000,0xbf6d3f35,0xbf6d3f80,0xbec43f35,
0x3f55bf80,0xbe48bec4,0xbf7b3f35,0xbf0e3f6d,0xbf0e0000,0xbf7b3f6d,0xbe483f35,0x3f55bec4,0xbf0e0000,0xbf7b3f6d,0xbe483f35,0x3f55bec4,
0xbf553f80,0x3e483ec4,0x3f7bbf35,0x3f0ebf6d,0xbf553f80,0x3e483ec4,0x3f7bbf35,0x3f0ebf6d,0x3f0e0000,0x3f7bbf6d,0x3e48bf35,0xbf553ec4,
0x3f0e0000,0x3f7bbf6d,0x3e48bf35,0xbf553ec4,0x3f55bf80,0xbe48bec4,0xbf7b3f35,0xbf0e3f6d,0xbf353f80,0x3f350000,0x3f35bf80,0xbf350000,
0xbf350000,0xbf353f80,0x3f350000,0x3f35bf80,0xbf353f80,0x3f350000,0x3f35bf80,0xbf350000,0xbf350000,0xbf353f80,0x3f350000,0x3f35bf80,
0xbf353f80,0x3f350000,0x3f35bf80,0xbf350000,0xbf350000,0xbf353f80,0x3f350000,0x3f35bf80,0xbf353f80,0x3f350000,0x3f35bf80,0xbf350000,
0xbf350000,0xbf353f80,0x3f350000,0x3f35bf80,0x3f550000,0x3e48bf6d,0xbf7b3f35,0x3f0e3ec4,0x3f0ebf80,0xbf7b3ec4,0x3e483f35,0x3f55bf6d,
0x3f0ebf80,0xbf7b3ec4,0x3e483f35,0x3f55bf6d,0xbf550000,0xbe483f6d,0x3f7bbf35,0xbf0ebec4,0xbf550000,0xbe483f6d,0x3f7bbf35,0xbf0ebec4,
0xbf0e3f80,0x3f7bbec4,0xbe48bf35,0xbf553f6d,0xbf0e3f80,0x3f7bbec4,0xbe48bf35,0xbf553f6d,0x3f550000,0x3e48bf6d,0xbf7b3f35,0x3f0e3ec4,
0x3ec4bf80,0xbf6d3f35,0x3f6d0000,0xbec4bf35,0x3f6d0000,0xbec4bf35,0xbec43f80,0x3f6dbf35,0xbec43f80,0x3f6dbf35,0xbf6d0000,0x3ec43f35,
0xbf6d0000,0x3ec43f35,0x3ec4bf80,0xbf6d3f35,0x3ec4bf80,0xbf6d3f35,0x3f6d0000,0xbec4bf35,0x3f6d0000,0xbec4bf35,0xbec43f80,0x3f6dbf35,
0xbec43f80,0x3f6dbf35,0xbf6d0000,0x3ec43f35,0xbf6d0000,0x3ec43f35,0x3ec4bf80,0xbf6d3f35,0xbe483f80,0x3f0ebf6d,0xbf553f35,0x3f7bbec4,
0x3f7b0000,0xbf55bec4,0x3f0e3f35,0xbe48bf6d,0x3f7b0000,0xbf55bec4,0x3f0e3f35,0xbe48bf6d,0x3e48bf80,0xbf0e3f6d,0x3f55bf35,0xbf7b3ec4,
0x3e48bf80,0xbf0e3f6d,0x3f55bf35,0xbf7b3ec4,0xbf7b0000,0x3f553ec4,0xbf0ebf35,0x3e483f6d,0xbf7b0000,0x3f553ec4,0xbf0ebf35,0x3e483f6d,
0xbe483f80,0x3f0ebf6d,0xbf553f35,0x3f7bbec4,0x80008000,0x80008000,0x80008000,0x80008000,0xbf803f80,0xbf803f80,0xbf803f80,0xbf803f80,
0x80008000,0x80008000,0x80008000,0x80008000,0xbf803f80,0xbf803f80,0xbf803f80,0xbf803f80,0x80008000,0x80008000,0x80008000,0x80008000,
0xbf803f80,0xbf803f80,0xbf803f80,0xbf803f80,0x80008000,0x80008000,0x80008000,0x80008000,0xbf803f80,0xbf803f80,0xbf803f80,0xbf803f80,
0xbf7b3f80,0xbf553f6d,0xbf0e3f35,0xbe483ec4,0x3e488000,0x3f0ebec4,0x3f55bf35,0x3f7bbf6d,0x3e480000,0x3f0ebec4,0x3f55bf35,0x3f7bbf6d,
0x3f7bbf80,0x3f55bf6d,0x3f0ebf35,0x3e48bec4,0x3f7bbf80,0x3f55bf6d,0x3f0ebf35,0x3e48bec4,0xbe488000,0xbf0e3ec4,0xbf553f35,0xbf7b3f6d,
0xbe480000,0xbf0e3ec4,0xbf553f35,0xbf7b3f6d,0xbf7b3f80,0xbf553f6d,0xbf0e3f35,0xbe483ec4,0xbec48000,0xbf6d3f35,0xbf6d3f80,0xbec43f35,
0x3f6dbf80,0x3ec4bf35,0xbec40000,0xbf6d3f35,0x3ec48000,0x3f6dbf35,0x3f6dbf80,0x3ec4bf35,0xbf6d3f80,0xbec43f35,0x3ec40000,0x3f6dbf35,
0xbec48000,0xbf6d3f35,0xbf6d3f80,0xbec43f35,0x3f6dbf80,0x3ec4bf35,0xbec40000,0xbf6d3f35,0x3ec48000,0x3f6dbf35,0x3f6dbf80,0x3ec4bf35,
0xbf6d3f80,0xbec43f35,0x3ec40000,0x3f6dbf35,0xbf0e0000,0xbf7b3f6d,0xbe483f35,0x3f55bec4,0xbf553f80,0x3e483ec4,0x3f7bbf35,0x3f0ebf6d,
0xbf553f80,0x3e483ec4,0x3f7bbf35,0x3f0ebf6d,0x3f0e8000,0x3f7bbf6d,0x3e48bf35,0xbf553ec4,0x3f0e0000,0x3f7bbf6d,0x3e48bf35,0xbf553ec4,
0x3f55bf80,0xbe48bec4,0xbf7b3f35,0xbf0e3f6d,0x3f55bf80,0xbe48bec4,0xbf7b3f35,0xbf0e3f6d,0xbf0e8000,0xbf7b3f6d,0xbe483f35,0x3f55bec4,
0x3f358000,0x3f35bf80,0xbf358000,0xbf353f80,0xbf353f80,0x3f350000,0x3f35bf80,0xbf350000,0x3f358000,0x3f35bf80,0xbf358000,0xbf353f80,
0xbf353f80,0x3f350000,0x3f35bf80,0xbf350000,0x3f358000,0x3f35bf80,0xbf358000,0xbf353f80,0xbf353f80,0x3f350000,0x3f35bf80,0xbf350000,
0x3f358000,0x3f35bf80,0xbf358000,0xbf353f80,0xbf353f80,0x3f350000,0x3f35bf80,0xbf350000,0x3f0ebf80,0xbf7b3ec4,0x3e483f35,0x3f55bf6d,
0xbf558000,0xbe483f6d,0x3f7bbf35,0xbf0ebec4,0xbf550000,0xbe483f6d,0x3f7bbf35,0xbf0ebec4,0xbf0e3f80,0x3f7bbec4,0xbe48bf35,0xbf553f6d,
0xbf0e3f80,0x3f7bbec4,0xbe48bf35,0xbf553f6d,0x3f558000,0x3e48bf6d,0xbf7b3f35,0x3f0e3ec4,0x3f550000,0x3e48bf6d,0xbf7b3f35,0x3f0e3ec4,
0x3f0ebf80,0xbf7b3ec4,0x3e483f35,0x3f55bf6d,0xbf6d8000,0x3ec43f35,0x3ec4bf80,0xbf6d3f35,0x3ec4bf80,0xbf6d3f35,0x3f6d0000,0xbec4bf35,
0x3f6d8000,0xbec4bf35,0xbec43f80,0x3f6dbf35,0xbec43f80,0x3f6dbf35,0xbf6d0000,0x3ec43f35,0xbf6d8000,0x3ec43f35,0x3ec4bf80,0xbf6d3f35,
0x3ec4bf80,0xbf6d3f35,0x3f6d0000,0xbec4bf35,0x3f6d8000,0xbec4bf35,0xbec43f80,0x3f6dbf35,0xbec43f80,0x3f6dbf35,0xbf6d0000,0x3ec43f35,
0x3f7b0000,0xbf55bec4,0x3f0e3f35,0xbe48bf6d,0x3e48bf80,0xbf0e3f6d,0x3f55bf35,0xbf7b3ec4,0x3e48bf80,0xbf0e3f6d,0x3f55bf35,0xbf7b3ec4,
0xbf7b8000,0x3f553ec4,0xbf0ebf35,0x3e483f6d,0xbf7b0000,0x3f553ec4,0xbf0ebf35,0x3e483f6d,0xbe483f80,0x3f0ebf6d,0xbf553f35,0x3f7bbec4,
0xbe483f80,0x3f0ebf6d,0xbf553f35,0x3f7bbec4,0x3f7b8000,0xbf55bec4,0x3f0e3f35,0xbe48bf6d,0x3f80,0xbf80,0x3f80,0xbf80,
0xbf800000,0x3f800000,0xbf800000,0x3f800000,0x3f80,0xbf80,0x3f80,0xbf80,0xbf800000,0x3f800000,0xbf800000,0x3f800000,
0x3f80,0xbf80,0x3f80,0xbf80,0xbf800000,0x3f800000,0xbf800000,0x3f800000,0x3f80,0xbf80,0x3f80,0xbf80,
0xbf800000,0x3f800000,0xbf800000,0x3f800000,0xbf7b0000,0x3f55bec4,0xbf0e3f35,0x3e48bf6d,0x3e483f80,0xbf0ebf6d,0x3f553f35,0xbf7bbec4,
0x3e483f80,0xbf0ebf6d,0x3f553f35,0xbf7bbec4,0x3f7b0000,0xbf553ec4,0x3f0ebf35,0xbe483f6d,0x3f7b0000,0xbf553ec4,0x3f0ebf35,0xbe483f6d,
0xbe48bf80,0x3f0e3f6d,0xbf55bf35,0x3f7b3ec4,0xbe48bf80,0x3f0e3f6d,0xbf55bf35,0x3f7b3ec4,0xbf7b0000,0x3f55bec4,0xbf0e3f35,0x3e48bf6d,
0xbec4bf80,0x3f6d3f35,0xbf6d0000,0x3ec4bf35,0x3f6d0000,0xbec43f35,0xbec4bf80,0x3f6d3f35,0x3ec43f80,0xbf6dbf35,0x3f6d0000,0xbec43f35,
0xbf6d0000,0x3ec4bf35,0x3ec43f80,0xbf6dbf35,0xbec4bf80,0x3f6d3f35,0xbf6d0000,0x3ec4bf35,0x3f6d0000,0xbec43f35,0xbec4bf80,0x3f6d3f35,
0x3ec43f80,0xbf6dbf35,0x3f6d0000,0xbec43f35,0xbf6d0000,0x3ec4bf35,0x3ec43f80,0xbf6dbf35,0xbf0ebf80,0x3f7b3ec4,0xbe483f35,0xbf55bf6d,
0xbf550000,0xbe48bf6d,0x3f7b3f35,0xbf0e3ec4,0xbf550000,0xbe48bf6d,0x3f7b3f35,0xbf0e3ec4,0x3f0e3f80,0xbf7bbec4,0x3e48bf35,0x3f553f6d,
0x3f0e3f80,0xbf7bbec4,0x3e48bf35,0x3f553f6d,0x3f550000,0x3e483f6d,0xbf7bbf35,0x3f0ebec4,0x3f550000,0x3e483f6d,0xbf7bbf35,0x3f0ebec4,
0xbf0ebf80,0x3f7b3ec4,0xbe483f35,0xbf55bf6d,0x3f353f80,0xbf350000,0xbf35bf80,0x3f350000,0xbf350000,0xbf35bf80,0x3f350000,0x3f353f80,
0x3f353f80,0xbf350000,0xbf35bf80,0x3f350000,0xbf350000,0xbf35bf80,0x3f350000,0x3f353f80,0x3f353f80,0xbf350000,0xbf35bf80,0x3f350000,
0xbf350000,0xbf35bf80,0x3f350000,0x3f353f80,0x3f353f80,0xbf350000,0xbf35bf80,0x3f350000,0xbf350000,0xbf35bf80,0x3f350000,0x3f353f80,
0x3f0e0000,0x3f7b3f6d,0x3e483f35,0xbf55bec4,0xbf55bf80,0x3e48bec4,0x3f7b3f35,0x3f0e3f6d,0xbf55bf80,0x3e48bec4,0x3f7b3f35,0x3f0e3f6d,
0xbf0e0000,0xbf7bbf6d,0xbe48bf35,0x3f553ec4,0xbf0e0000,0xbf7bbf6d,0xbe48bf35,0x3f553ec4,0x3f553f80,0xbe483ec4,0xbf7bbf35,0xbf0ebf6d,
0x3f553f80,0xbe483ec4,0xbf7bbf35,0xbf0ebf6d,0x3f0e0000,0x3f7b3f6d,0x3e483f35,0xbf55bec4,0xbf6dbf80,0xbec4bf35,0x3ec40000,0x3f6d3f35,
0x3ec40000,0x3f6d3f35,0x3f6d3f80,0x3ec43f35,0x3f6d3f80,0x3ec43f35,0xbec40000,0xbf6dbf35,0xbec40000,0xbf6dbf35,0xbf6dbf80,0xbec4bf35,
0xbf6dbf80,0xbec4bf35,0x3ec40000,0x3f6d3f35,0x3ec40000,0x3f6d3f35,0x3f6d3f80,0x3ec43f35,0x3f6d3f80,0x3ec43f35,0xbec40000,0xbf6dbf35,
0xbec40000,0xbf6dbf35,0xbf6dbf80,0xbec4bf35,0x3f7b3f80,0x3f553f6d,0x3f0e3f35,0x3e483ec4,0x3e480000,0x3f0e3ec4,0x3f553f35,0x3f7b3f6d,
0x3e480000,0x3f0e3ec4,0x3f553f35,0x3f7b3f6d,0xbf7bbf80,0xbf55bf6d,0xbf0ebf35,0xbe48bec4,0xbf7bbf80,0xbf55bf6d,0xbf0ebf35,0xbe48bec4,
0xbe480000,0xbf0ebec4,0xbf55bf35,0xbf7bbf6d,0xbe480000,0xbf0ebec4,0xbf55bf35,0xbf7bbf6d,0x3f7b3f80,0x3f553f6d,0x3f0e3f35,0x3e483ec4,
0x3f808000,0xbf808000,0x3f808000,0xbf808000,0x3f80,0xbf80,0x3f80,0xbf80,0x3f808000,0xbf808000,0x3f808000,0xbf808000,
0x3f80,0xbf80,0x3f80,0xbf80,0x3f808000,0xbf808000,0x3f808000,0xbf808000,0x3f80,0xbf80,0x3f80,0xbf80,
0x3f808000,0xbf808000,0x3f808000,0xbf808000,0x3f80,0xbf80,0x3f80,0xbf80,0x3e483f80,0xbf0ebf6d,0x3f553f35,0xbf7bbec4,
0x3f7b8000,0xbf553ec4,0x3f0ebf35,0xbe483f6d,0x3f7b0000,0xbf553ec4,0x3f0ebf35,0xbe483f6d,0xbe48bf80,0x3f0e3f6d,0xbf55bf35,0x3f7b3ec4,
0xbe48bf80,0x3f0e3f6d,0xbf55bf35,0x3f7b3ec4,0xbf7b8000,0x3f55bec4,0xbf0e3f35,0x3e48bf6d,0xbf7b0000,0x3f55bec4,0xbf0e3f35,0x3e48bf6d,
0x3e483f80,0xbf0ebf6d,0x3f553f35,0xbf7bbec4,0xbf6d8000,0x3ec4bf35,0x3ec43f80,0xbf6dbf35,0xbec4bf80,0x3f6d3f35,0xbf6d0000,0x3ec4bf35,
0x3f6d8000,0xbec43f35,0xbec4bf80,0x3f6d3f35,0x3ec43f80,0xbf6dbf35,0x3f6d0000,0xbec43f35,0xbf6d8000,0x3ec4bf35,0x3ec43f80,0xbf6dbf35,
0xbec4bf80,0x3f6d3f35,0xbf6d0000,0x3ec4bf35,0x3f6d8000,0xbec43f35,0xbec4bf80,0x3f6d3f35,0x3ec43f80,0xbf6dbf35,0x3f6d0000,0xbec43f35,
0xbf550000,0xbe48bf6d,0x3f7b3f35,0xbf0e3ec4,0x3f0e3f80,0xbf7bbec4,0x3e48bf35,0x3f553f6d,0x3f0e3f80,0xbf7bbec4,0x3e48bf35,0x3f553f6d,
0x3f558000,0x3e483f6d,0xbf7bbf35,0x3f0ebec4,0x3f550000,0x3e483f6d,0xbf7bbf35,0x3f0ebec4,0xbf0ebf80,0x3f7b3ec4,0xbe483f35,0xbf55bf6d,
0xbf0ebf80,0x3f7b3ec4,0xbe483f35,0xbf55bf6d,0xbf558000,0xbe48bf6d,0x3f7b3f35,0xbf0e3ec4,0x3f358000,0x3f353f80,0xbf358000,0xbf35bf80,
0x3f353f80,0xbf350000,0xbf35bf80,0x3f350000,0x3f358000,0x3f353f80,0xbf358000,0xbf35bf80,0x3f353f80,0xbf350000,0xbf35bf80,0x3f350000,
0x3f358000,0x3f353f80,0xbf358000,0xbf35bf80,0x3f353f80,0xbf350000,0xbf35bf80,0x3f350000,0x3f358000,0x3f353f80,0xbf358000,0xbf35bf80,
0x3f353f80,0xbf350000,0xbf35bf80,0x3f350000,0xbf55bf80,0x3e48bec4,0x3f7b3f35,0x3f0e3f6d,0xbf0e8000,0xbf7bbf6d,0xbe48bf35,0x3f553ec4,
0xbf0e0000,0xbf7bbf6d,0xbe48bf35,0x3f553ec4,0x3f553f80,0xbe483ec4,0xbf7bbf35,0xbf0ebf6d,0x3f553f80,0xbe483ec4,0xbf7bbf35,0xbf0ebf6d,
0x3f0e8000,0x3f7b3f6d,0x3e483f35,0xbf55bec4,0x3f0e0000,0x3f7b3f6d,0x3e483f35,0xbf55bec4,0xbf55bf80,0x3e48bec4,0x3f7b3f35,0x3f0e3f6d,
0xbec48000,0xbf6dbf35,0xbf6dbf80,0xbec4bf35,0xbf6dbf80,0xbec4bf35,0x3ec40000,0x3f6d3f35,0x3ec48000,0x3f6d3f35,0x3f6d3f80,0x3ec43f35,
0x3f6d3f80,0x3ec43f35,0xbec40000,0xbf6dbf35,0xbec48000,0xbf6dbf35,0xbf6dbf80,0xbec4bf35,0xbf6dbf80,0xbec4bf35,0x3ec40000,0x3f6d3f35,
0x3ec48000,0x3f6d3f35,0x3f6d3f80,0x3ec43f35,0x3f6d3f80,0x3ec43f35,0xbec40000,0xbf6dbf35,0x3e480000,0x3f0e3ec4,0x3f553f35,0x3f7b3f6d,
0xbf7bbf80,0xbf55bf6d,0xbf0ebf35,0xbe48bec4,0xbf7bbf80,0xbf55bf6d,0xbf0ebf35,0xbe48bec4,0xbe488000,0xbf0ebec4,0xbf55bf35,0xbf7bbf6d,
0xbe480000,0xbf0ebec4,0xbf55bf35,0xbf7bbf6d,0x3f7b3f80,0x3f553f6d,0x3f0e3f35,0x3e483ec4,0x3f7b3f80,0x3f553f6d,0x3f0e3f35,0x3e483ec4,
0x3e488000,0x3f0e3ec4,0x3f553f35,0x3f7b3f6d,
};
__device__ __align__(1024) uint8_t g_hT[32 * 262144];
__device__ __align__(1024) bf16 g_U[128 * 2 * 8 * 1024];
__device__ __align__(128) float g_gp[128 * 256];
__device__ __align__(128) uint4 g_agg[16 * 512];
#define CS 32
#define NREP 1
#define NREPH 4
constexpr int RS = 9 * CS;
__device__ __align__(128) unsigned g_cnt[32 * RS];
constexpr int CNT_U = 0, CNT_V = 1, CNT_DONE = 2, CNT_EPOCH = 3, CNT_H = 4  ;
#define PROFK(i) do { } while (0)
#define PROFC(i) do { } while (0)
#define PROF(i) do { } while (0)
#define PROFX(i) do { } while (0)
#define PROFR(i) do { } while (0)
#define PROFT(i) do { } while (0)
#define PROFS(i) do { } while (0)
#define PROFG(i) do { } while (0)

constexpr int SLOT = 32768;
constexpr int OFF_HS = 4 * SLOT;
constexpr int OFF_W = OFF_HS + 16384;
constexpr int OFF_F = OFF_W + 2 * 18432;
constexpr int OFF_G = OFF_F + 8192;
constexpr int OFF_K = OFF_G + 1024;
constexpr int OFF_GW = OFF_K + 2048;
constexpr int OFF_U = 6 * SLOT;
constexpr int OFF_BAR = OFF_U + 32768;
constexpr int OFF_SC = OFF_BAR + 384;
constexpr int OFF_KEPT = OFF_SC + 1024;
constexpr int OFF_PROF = OFF_KEPT + 64;
constexpr int SMEM_BYTES = OFF_PROF;
constexpr int BAR_FULL = 0  , BAR_U = 11, BAR_W = 12  , BAR_F = 14  ,
              BAR_EMPTY = 17  , BAR_HW = 22  , BAR_WR = 25, BAR_VW = 26, BAR_S1 = 27,
              BAR_XC = 28  , BAR_HR = 32,
              BAR_C = 34  , BAR_HD = 36  ;

#define DEVI __device__ __forceinline__
constexpr unsigned SPIN_LIMIT = 1u << 22;

DEVI uint32_t smem_u32(const void* p) { return (uint32_t)__cvta_generic_to_shared(p); }
DEVI uint64_t gtime() { uint64_t t; asm volatile("mov.u64 %0, %%globaltimer;" : "=l"(t)); return t; }
DEVI void mbar_init(uint32_t bar, uint32_t cnt) { asm volatile("mbarrier.init.shared::cta.b64 [%0], %1;" :: "r"(bar), "r"(cnt) : "memory"); }
DEVI void mbar_expect_tx(uint32_t bar, uint32_t bytes) { asm volatile("mbarrier.arrive.expect_tx.shared::cta.b64 _, [%0], %1;" :: "r"(bar), "r"(bytes) : "memory"); }
DEVI void mbar_arrive(uint32_t bar) { asm volatile("mbarrier.arrive.shared::cta.b64 _, [%0];" :: "r"(bar) : "memory"); }
#define WAIT_LOOP "{\n.reg .pred p;\n.reg .u32 n;\nmov.u32 n, 0;\n" \
                  "LW:\nmbarrier.try_wait.parity.shared::cta.b64 p, [%0], %1;\n@p bra LD;\n" \
                  "add.u32 n, n, 1;\nsetp.lt.u32 p, n, 131072;\n@p bra LW;\nLD:\n"
DEVI void mbar_wait(uint32_t bar, uint32_t parity) { asm volatile(WAIT_LOOP "}" :: "r"(bar), "r"(parity) : "memory"); }
DEVI void warp_arrive(uint32_t bar) { asm volatile("{\n.reg .pred p;\nelect.sync _|p, 0xffffffff;\n@p mbarrier.arrive.shared::cta.b64 _, [%0];\n}" :: "r"(bar) : "memory"); }
DEVI bool elect() {
    uint32_t p;
    asm volatile("{\n.reg .pred P;\nelect.sync _|P, 0xffffffff;\nselp.u32 %0, 1, 0, P;\n}" : "=r"(p));
    return p;
}
DEVI void fence_barrier_init() { asm volatile("fence.mbarrier_init.release.cluster;" ::: "memory"); }
DEVI void fence_proxy_async_smem() { asm volatile("fence.proxy.async.shared::cta;" ::: "memory"); }
#define HF 1
#define FPOS 0
DEVI void helper_sync() { asm volatile("bar.sync 1, 128;" ::: "memory"); }

DEVI void pause(unsigned n) {
    asm volatile("{\n.reg .pred p;\n.reg .u32 a, b;\nmov.u32 a, %%clock;\n"
                 "LP:\nmov.u32 b, %%clock;\nsub.u32 b, b, a;\nsetp.lt.u32 p, b, %0;\n@p bra LP;\n}" :: "r"(n) : "memory");
}
DEVI void sched_fence() { asm volatile("{\n.reg .pred p;\n.reg .b32 n;\nLP:\nactivemask.b32 n;\nsetp.eq.u32 p, n, 0;\n@p bra LP;\n}" ::: "memory"); }
#define P_POLL 0
#define NPOLL 1
DEVI void wait_counter(const unsigned* p, unsigned target) {
    unsigned v[NPOLL];
    auto ld = [&](int i) { asm volatile("ld.relaxed.gpu.global.u32 %0, [%1];" : "=r"(v[i]) : "l"(p) : "memory"); };
#pragma unroll
    for (int i = 0; i < NPOLL; i++) { if (i) pause(200); ld(i); }
#pragma unroll 1
    for (unsigned n = 0; n < SPIN_LIMIT; n++) {
#pragma unroll
        for (int i = 0; i < NPOLL; i++) {
            if ((int)(v[i] - target) >= 0) return;
            if (P_POLL) pause(P_POLL);
            ld(i);
        }
    }
}
DEVI void signal_counter(unsigned* p) {
#pragma unroll
    for (int r = 0; r < NREP; r++) asm volatile("red.relaxed.gpu.global.add.u32 [%0], 1;" :: "l"(p + r * RS) : "memory");
}

DEVI void tma_load_3d(uint32_t dst, const CUtensorMap* map, uint32_t bar, int c0, int c1, int c2) {
    asm volatile("cp.async.bulk.tensor.3d.shared::cluster.global.mbarrier::complete_tx::bytes [%0], [%1, {%3, %4, %5}], [%2];"
        :: "r"(dst), "l"(map), "r"(bar), "r"(c0), "r"(c1), "r"(c2) : "memory");
}
DEVI void tma_load_4d(uint32_t dst, const CUtensorMap* map, uint32_t bar, int c0, int c1, int c2, int c3) {
    asm volatile("cp.async.bulk.tensor.4d.shared::cluster.global.mbarrier::complete_tx::bytes [%0], [%1, {%3, %4, %5, %6}], [%2];"
        :: "r"(dst), "l"(map), "r"(bar), "r"(c0), "r"(c1), "r"(c2), "r"(c3) : "memory");
}
DEVI void tma_load_5d(uint32_t dst, const CUtensorMap* map, uint32_t bar, int c0, int c3, int c4) {
    asm volatile("cp.async.bulk.tensor.5d.shared::cluster.global.mbarrier::complete_tx::bytes [%0], [%1, {%3, %6, %6, %4, %5}], [%2];"
        :: "r"(dst), "l"(map), "r"(bar), "r"(c0), "r"(c3), "r"(c4), "r"(0) : "memory");
}
DEVI void tma_store_4d(const CUtensorMap* map, uint32_t src, int c0, int c1, int c2, int c3) {
    asm volatile("cp.async.bulk.tensor.4d.global.shared::cta.bulk_group [%0, {%2, %3, %4, %5}], [%1];"
        :: "l"(map), "r"(src), "r"(c0), "r"(c1), "r"(c2), "r"(c3) : "memory");
}
DEVI void bulk_load(uint32_t dst, const void* src, uint32_t bytes, uint32_t bar) {
    asm volatile("cp.async.bulk.shared::cluster.global.mbarrier::complete_tx::bytes [%0], [%1], %2, [%3];"
        :: "r"(dst), "l"(src), "r"(bytes), "r"(bar) : "memory");
}
DEVI void bulk_prefetch_l2(const void* src, uint32_t bytes) {
    asm volatile("cp.async.bulk.prefetch.L2.global [%0], %1;" :: "l"(src), "r"(bytes) : "memory");
}
DEVI void tma_store_3d(const CUtensorMap* map, uint32_t src, int c0, int c1, int c2) {
    asm volatile("cp.async.bulk.tensor.3d.global.shared::cta.bulk_group [%0, {%2, %3, %4}], [%1];"
        :: "l"(map), "r"(src), "r"(c0), "r"(c1), "r"(c2) : "memory");
}
DEVI void bulk_store(void* dst, uint32_t src, uint32_t bytes) {
    asm volatile("cp.async.bulk.global.shared::cta.bulk_group [%0], [%1], %2;" :: "l"(dst), "r"(src), "r"(bytes) : "memory");
}
DEVI void bulk_commit() { asm volatile("cp.async.bulk.commit_group;" ::: "memory"); }
DEVI void bulk_wait0() { asm volatile("cp.async.bulk.wait_group 0;" ::: "memory"); }

DEVI void wgmma_fence() { asm volatile("wgmma.fence.sync.aligned;" ::: "memory"); }
DEVI void wgmma_commit() { asm volatile("wgmma.commit_group.sync.aligned;" ::: "memory"); }
template<int N> DEVI void wgmma_wait() { asm volatile("wgmma.wait_group.sync.aligned %0;" :: "n"(N) : "memory"); }
template<int N> DEVI void wgmma_wait_all(float (&d)[N]) {
    wgmma_wait<0>();
#pragma unroll
    for (int i = 0; i < N; i++) asm volatile("" : "+f"(d[i]) :: "memory");
}
template<int R> DEVI void reg_alloc() { asm volatile("setmaxnreg.inc.sync.aligned.u32 %0;" :: "n"(R)); }
template<int R> DEVI void reg_dealloc() { asm volatile("setmaxnreg.dec.sync.aligned.u32 %0;" :: "n"(R)); }

constexpr uint32_t SB0 = 1024;
DEVI uint64_t make_desc(uint32_t off, uint32_t lbo, uint32_t sbo, uint32_t mode = 1) {
    return (uint64_t)(((SB0 + off) >> 4) | ((lbo >> 4) << 16)) | ((uint64_t)((sbo >> 4) | (mode << 30)) << 32);
}

#define ACC8(a, o) "+f"(a[o+0]), "+f"(a[o+1]), "+f"(a[o+2]), "+f"(a[o+3]), "+f"(a[o+4]), "+f"(a[o+5]), "+f"(a[o+6]), "+f"(a[o+7])
#define OUT8(a, o) "=f"(a[o+0]), "=f"(a[o+1]), "=f"(a[o+2]), "=f"(a[o+3]), "=f"(a[o+4]), "=f"(a[o+5]), "=f"(a[o+6]), "=f"(a[o+7])
#define ACC32(a, o) ACC8(a, o), ACC8(a, o+8), ACC8(a, o+16), ACC8(a, o+24)

#define SS_N128 "{\n.reg .pred p;\nsetp.ne.b32 p, %66, 0;\n" \
        "wgmma.mma_async.sync.aligned.m64n128k16.f32.bf16.bf16 " \
        "{%0, %1, %2, %3, %4, %5, %6, %7, %8, %9, %10, %11, %12, %13, %14, %15, " \
        "%16, %17, %18, %19, %20, %21, %22, %23, %24, %25, %26, %27, %28, %29, %30, %31, " \
        "%32, %33, %34, %35, %36, %37, %38, %39, %40, %41, %42, %43, %44, %45, %46, %47, " \
        "%48, %49, %50, %51, %52, %53, %54, %55, %56, %57, %58, %59, %60, %61, %62, %63}, " \
        "%64, %65, p, 1, 1, %67, %68;\n}\n"
template<int TA, int TB>
DEVI void wgmma_n128(float (&d)[64], uint64_t da, uint64_t db, int scale_d) {
    asm volatile(SS_N128 : ACC32(d, 0), ACC32(d, 32) : "l"(da), "l"(db), "r"(scale_d), "n"(TA), "n"(TB));
}
DEVI void wgmma_n128_set(float (&d)[64], uint64_t da, uint64_t db) {
    asm volatile(SS_N128 : OUT8(d, 0), OUT8(d, 8), OUT8(d, 16), OUT8(d, 24), OUT8(d, 32), OUT8(d, 40), OUT8(d, 48), OUT8(d, 56) : "l"(da), "l"(db), "n"(0), "n"(0), "n"(1));
}
#define SS_N16 "{\n.reg .pred p;\nsetp.ne.b32 p, 0, 0;\n" \
        "wgmma.mma_async.sync.aligned.m64n16k16.f32.bf16.bf16 " \
        "{%0, %1, %2, %3, %4, %5, %6, %7}, %8, %9, p, 1, 1, %10, 0;\n}\n"
template<int TA> DEVI void wgmma_n16(float* d, uint64_t da, uint64_t db) {
    asm volatile(SS_N16 : OUT8(d, 0) : "l"(da), "l"(db), "n"(TA));
}
#define SS_N8 "{\n.reg .pred p;\nsetp.ne.b32 p, %6, 0;\n" \
        "wgmma.mma_async.sync.aligned.m64n8k16.f32.bf16.bf16 {%0, %1, %2, %3}, %4, %5, p, 1, 1, 0, 0;\n}\n"
DEVI void wgmma_n8(float (&d)[4], uint64_t da, uint64_t db, bool add) {
    if (add) asm volatile(SS_N8 : "+f"(d[0]), "+f"(d[1]), "+f"(d[2]), "+f"(d[3]) : "l"(da), "l"(db), "n"(1));
    else asm volatile(SS_N8 : "=f"(d[0]), "=f"(d[1]), "=f"(d[2]), "=f"(d[3]) : "l"(da), "l"(db), "n"(0));
}
#define RS_N64 "{\n.reg .pred p;\nsetp.ne.b32 p, %37, 0;\n" \
        "wgmma.mma_async.sync.aligned.m64n64k16.f32.bf16.bf16 " \
        "{%0, %1, %2, %3, %4, %5, %6, %7, %8, %9, %10, %11, %12, %13, %14, %15, " \
        "%16, %17, %18, %19, %20, %21, %22, %23, %24, %25, %26, %27, %28, %29, %30, %31}, " \
        "{%32, %33, %34, %35}, %36, p, 1, 1, %38;\n}\n"
template<int SCALE_D, int TB = 0>
DEVI void wgmma_rs_n64(float (&d)[32], const uint32_t (&a)[4], uint64_t db) {
    if (SCALE_D) asm volatile(RS_N64 : ACC32(d, 0) : "r"(a[0]), "r"(a[1]), "r"(a[2]), "r"(a[3]), "l"(db), "n"(1), "n"(TB));
    else asm volatile(RS_N64 : OUT8(d, 0), OUT8(d, 8), OUT8(d, 16), OUT8(d, 24) : "r"(a[0]), "r"(a[1]), "r"(a[2]), "r"(a[3]), "l"(db), "n"(0), "n"(TB));
}
#define SS_N64 "{\n.reg .pred p;\nsetp.ne.b32 p, %34, 0;\n" \
        "wgmma.mma_async.sync.aligned.m64n64k16.f32.bf16.bf16 " \
        "{%0, %1, %2, %3, %4, %5, %6, %7, %8, %9, %10, %11, %12, %13, %14, %15, " \
        "%16, %17, %18, %19, %20, %21, %22, %23, %24, %25, %26, %27, %28, %29, %30, %31}, " \
        "%32, %33, p, 1, 1, 0, 1;\n}\n"
template<int SCALE_D> DEVI void wgmma_ss_n64(float (&d)[32], uint64_t da, uint64_t db) {
    if (SCALE_D) asm volatile(SS_N64 : ACC32(d, 0) : "l"(da), "l"(db), "n"(1));
    else asm volatile(SS_N64 : OUT8(d, 0), OUT8(d, 8), OUT8(d, 16), OUT8(d, 24) : "l"(da), "l"(db), "n"(0));
}
DEVI void ldsm_x4_t(uint32_t (&r)[4], uint32_t addr) {
    asm volatile("ldmatrix.sync.aligned.m8n8.x4.trans.shared.b16 {%0, %1, %2, %3}, [%4];"
        : "=r"(r[0]), "=r"(r[1]), "=r"(r[2]), "=r"(r[3]) : "r"(addr) : "memory");
}
DEVI void ldsm_x4(uint32_t (&r)[4], uint32_t addr) {
    asm volatile("ldmatrix.sync.aligned.m8n8.x4.shared.b16 {%0, %1, %2, %3}, [%4];"
        : "=r"(r[0]), "=r"(r[1]), "=r"(r[2]), "=r"(r[3]) : "r"(addr) : "memory");
}
DEVI void stsm_x4(uint32_t addr, uint32_t r0, uint32_t r1, uint32_t r2, uint32_t r3) {
    asm volatile("stmatrix.sync.aligned.m8n8.x4.shared.b16 [%0], {%1, %2, %3, %4};"
        :: "r"(addr), "r"(r0), "r"(r1), "r"(r2), "r"(r3) : "memory");
}
DEVI void stsm_x4_t(uint32_t addr, uint32_t r0, uint32_t r1, uint32_t r2, uint32_t r3) {
    asm volatile("stmatrix.sync.aligned.m8n8.x4.trans.shared.b16 [%0], {%1, %2, %3, %4};"
        :: "r"(addr), "r"(r0), "r"(r1), "r"(r2), "r"(r3) : "memory");
}
DEVI uint32_t movm(uint32_t a) { uint32_t d; asm volatile("movmatrix.sync.aligned.m8n8.trans.b16 %0, %1;" : "=r"(d) : "r"(a)); return d; }
DEVI uint32_t pack2(float lo, float hi) { uint32_t d; asm("cvt.rn.bf16x2.f32 %0, %1, %2;" : "=r"(d) : "f"(hi), "f"(lo)); return d; }
DEVI float bf_lo(uint32_t v) { return __uint_as_float(v << 16); }
DEVI float bf_hi(uint32_t v) { return __uint_as_float(v & 0xffff0000u); }
DEVI float bf_round(float v) { return __bfloat162float(__float2bfloat16_rn(v)); }
DEVI uint32_t bf_mul2(uint32_t a, uint32_t b) { uint32_t d; asm("mul.rn.bf16x2 %0, %1, %2;" : "=r"(d) : "r"(a), "r"(b)); return d; }
DEVI uint32_t bf_add2(uint32_t a, uint32_t b) { uint32_t d; asm("add.rn.bf16x2 %0, %1, %2;" : "=r"(d) : "r"(a), "r"(b)); return d; }
DEVI uint32_t bf_sub2(uint32_t a, uint32_t b) { uint32_t d; asm("sub.rn.bf16x2 %0, %1, %2;" : "=r"(d) : "r"(a), "r"(b)); return d; }
DEVI uint4 lds128u(uint32_t a) { uint4 v; asm volatile("ld.shared.v4.u32 {%0, %1, %2, %3}, [%4];" : "=r"(v.x), "=r"(v.y), "=r"(v.z), "=r"(v.w) : "r"(a) : "memory"); return v; }
DEVI void sts128u(uint32_t a, uint32_t x, uint32_t y, uint32_t z, uint32_t w) { asm volatile("st.shared.v4.u32 [%0], {%1, %2, %3, %4};" :: "r"(a), "r"(x), "r"(y), "r"(z), "r"(w) : "memory"); }
DEVI uint2 lds64u(uint32_t a) { uint2 v; asm volatile("ld.shared.v2.u32 {%0, %1}, [%2];" : "=r"(v.x), "=r"(v.y) : "r"(a) : "memory"); return v; }
DEVI uint32_t ldg32u(const void* p) { uint32_t v; asm volatile("ld.global.nc.u32 %0, [%1];" : "=r"(v) : "l"(p) : "memory"); return v; }
DEVI void sts64(uint32_t a, float x, float y) { asm volatile("st.shared.v2.f32 [%0], {%1, %2};" :: "r"(a), "f"(x), "f"(y) : "memory"); }
DEVI void sts32(uint32_t a, uint32_t v) { asm volatile("st.shared.u32 [%0], %1;" :: "r"(a), "r"(v) : "memory"); }
DEVI uint32_t lds16(uint32_t a) { uint32_t v; asm volatile("ld.shared.u16 %0, [%1];" : "=r"(v) : "r"(a) : "memory"); return v; }
DEVI void cmul2(uint32_t& x, uint32_t& y, uint32_t c, uint32_t s, uint32_t n) {
    asm("{\n.reg .b32 t, u;\nmul.rn.bf16x2 t, %1, %4;\nmul.rn.bf16x2 u, %1, %2;\n"
        "fma.rn.bf16x2 %1, %0, %3, u;\nfma.rn.bf16x2 %0, %0, %2, t;\n}" : "+r"(x), "+r"(y) : "r"(c), "r"(s), "r"(n));
}
DEVI uint32_t neg2(uint32_t s) { uint32_t n; asm volatile("xor.b32 %0, %1, 0x80008000;" : "=r"(n) : "r"(s)); return n; }
DEVI void cmul2(uint32_t& x, uint32_t& y, uint32_t c, uint32_t s) { cmul2(x, y, c, s, neg2(s)); }
DEVI void cmul2c(uint32_t& x, uint32_t& y, uint32_t c, uint32_t s) { cmul2(x, y, c, neg2(s), s); }
DEVI void sts16(uint32_t a, float v) { asm volatile("st.shared.u16 [%0], %1;" :: "r"(a), "r"(pack2(v, v)) : "memory"); }

DEVI float2 cmul(float2 a, float2 b) { return make_float2(fmaf(a.x, b.x, -a.y * b.y), fmaf(a.x, b.y, a.y * b.x)); }
DEVI float2 cfma(float2 a, float2 b, float2 c) { return make_float2(fmaf(a.x, b.x, fmaf(-a.y, b.y, c.x)), fmaf(a.x, b.y, fmaf(a.y, b.x, c.y))); }

DEVI float2 csq(float2 a) {
    float y;
    asm("{\n.reg .f32 t;\nmul.ftz.f32 t, %1, %2;\nmul.ftz.f32 %0, t, 0f40000000;\n}" : "=f"(y) : "f"(a.x), "f"(a.y));
    return make_float2(fmaf(a.x, a.x, -a.y * a.y), y);
}

struct Params {
    const bf16 *lam_re, *lam_im, *log_dt, *dskip, *gate_w, *c_re, *c_im, *b_re, *b_im, *x;
    int swapB;
};

#define R8_POLL 8
#define R8B 1
#define SCB 32
#define C0 1
#define R8A 4
DEVI void radix8(uint32_t sb, bool inv, int w, int lane, int bar) {
    const uint64_t dg = make_desc(OFF_G + (inv ? 512 : 0), 128, 256, 0), da = make_desc(OFF_U, 16, 16384);
    float acc[2][64];
    wgmma_fence();
#pragma unroll
    for (int j = 0; j < 8; j++) wgmma_n16<1>(acc[0] + 8 * j, da + 64 * j, dg);
    wgmma_commit();
    sched_fence();
    asm volatile("" : "+r"(lane));
    const int kk = lane & 7, ch = 2 * w + ((lane >> 3) & 1);
    const uint32_t st = sb + OFF_U + (inv ? (lane >> 4) * 16384 + kk * 128 + ((ch ^ kk) << 4)
        : (kk & 1) * 16384 + (kk >> 2) * 2048 + (lane >> 4) * 1024 + (w >> 1) * 128 + ((((kk & 2) * 2 + ((ch & 3) ^ (kk >> 2) ^ (2 * (kk & 1)))) ^ (w >> 1)) << 4));
    uint32_t sa[4];
#pragma unroll
    for (int i = 0; i < 4; i++) { sa[i] = inv ? (st ^ (i << 4)) + i * 1024 : (st ^ (i << 5)) + i * 256; asm volatile("" : "+r"(sa[i])); }
    const int warp = inv;
    sched_fence();
    if (R8A) {
        wgmma_fence();
#pragma unroll
        for (int j = 0; j < R8A; j++) wgmma_n16<1>(acc[1] + 8 * j, da + 64 * (8 + j), dg);
        wgmma_commit();
    }
    PROFC(8);
#pragma unroll
    for (int i = 0; i < 2; i++) {
        if (i || !R8A) wgmma_wait<0>(); else wgmma_wait<1>();
#pragma unroll
        for (int j = 0; j < 64; j++) asm volatile("" : "+f"(acc[i][j]) :: "memory");
        PROFC(9 + 2 * i);
        asm volatile("bar.sync %0, 128;" :: "r"(bar) : "memory");
        if (!i && R8A < 8) wgmma_fence();
#pragma unroll
        for (int j = 0; j < 8; j++) {
            const float* a = acc[i] + 8 * j;
            if (!i && j + R8A < 8) wgmma_n16<1>(acc[1] + 8 * (j + R8A), da + 64 * (8 + j + R8A), dg);
            stsm_x4_t(sa[j & 3] + (2 * i + (j >> 2)) * 4096, pack2(a[0], a[1]), pack2(a[2], a[3]), pack2(a[4], a[5]), pack2(a[6], a[7]));
        }
        if (!i && R8A < 8) wgmma_commit();
        PROFC(10 + 2 * i);
        if (i ? inv || !(FPOS & 1) : inv && HF) fence_proxy_async_smem();
        __syncwarp();
        if (inv) warp_arrive(sb + OFF_BAR + 8 * BAR_VW);
    }
}

template<int N> DEVI void c_take(float (&acc)[32], uint32_t (&p)[16]) {
    wgmma_wait<N>();
#pragma unroll
    for (int i = 0; i < 32; i++) asm volatile("" : "+f"(acc[i]) :: "memory");
#pragma unroll
    for (int i = 0; i < 16; i++) p[i] = pack2(acc[2 * i], acc[2 * i + 1]);
}
DEVI uint64_t desc_at(uint64_t d, uint32_t o) { return (d & 0xffffffff00000000ull) | ((uint32_t)d + o); }
DEVI void c_cols(float (&acc)[32], uint64_t df, uint64_t db, int o) {
    wgmma_fence();
    wgmma_ss_n64<0>(acc, df, desc_at(db, o));
#pragma unroll
    for (int s = 1; s < 4; s++) wgmma_ss_n64<1>(acc, df + 2 * s, desc_at(db, o + 256 * s));
    wgmma_commit();
}

DEVI void phase_c(uint32_t sb, int ps, bool rot, int w, int lane) {
    const int warp = ps, bar = 5 + ps;
    PROFC(0);
    const uint32_t rb = sb + OFF_U + ps * 16384;
    const uint64_t df = make_desc(OFF_F, 16, 1024), db = make_desc(OFF_U + ps * 16384, 16, 1024);
    float acc[2][32];
    c_cols(acc[0], df, db, 0);
    c_cols(acc[1], df, db, 128);
    sched_fence();
    asm volatile("" : "+r"(lane));
    const int g = lane & 7, l3 = (lane >> 3) & 1, l4 = lane >> 4;
    uint32_t wf[2][4][4];
    const uint32_t wo = sb + OFF_W + (1 - ps) * 18432 + l4 * 9216 + g * 64 + ((w ^ (g >> 1)) << 4);
    uint32_t wd = wo + l3 * 1152, wm[2] = {wo + 4608 + (((rot ? 4 : 3) - l3) & 3) * 1152, wo + 4608 + ((rot ? 2 : 1) - l3) * 1152};
    uint32_t xa = rb + w * 4096 + l4 * 1024 + g * 128 + (((4 * l3) ^ g) << 4);
    uint32_t oa = rb + (4 * w + (g >> 1)) * 1024 + (1 - l3) * 512 + (((4 * (g & 1) + l4) ^ (4 - 4 * l3) ^ (g >> 1)) << 4);
    auto load_w = [&](int h) {
#pragma unroll
        for (int j = 0; j < 4; j++) ldsm_x4_t(wf[h][j], (j < 2 ? wd + h * 2304 : wm[h]) + (j & 1) * 512);
    };
    uint32_t tw[8][3];
    {
        const float a0 = (float)(8 * w + (lane >> 2)) * 0.0061359231515425649f, q2 = (float)(2 * (lane & 3)), p16 = (float)(16 * ps);
        const float b0 = a0 * (q2 + p16), b1 = a0 * (q2 - p16);
#pragma unroll
        for (int j = 0; j < 4; j++) {
            const float u = fmaf(a0, 8.f * j, j < 2 ? b0 : b1), v = u + a0, su = __sinf(u), sv = __sinf(v);
            tw[j][0] = pack2(__cosf(u), __cosf(v)); tw[j][1] = pack2(-su, -sv); tw[j][2] = pack2(su, sv);
        }
    }
#pragma unroll
    for (int j = 0; j < 4; j++) asm volatile("" : "+r"(tw[j][0]), "+r"(tw[j][1]), "+r"(tw[j][2]));
    asm volatile("" : "+r"(wd), "+r"(wm[0]), "+r"(wm[1]), "+r"(xa), "+r"(oa));
    sched_fence();
    auto twiddle = [&](uint32_t& x, uint32_t& y, int j) { cmul2(x, y, tw[j][0], tw[j][1], tw[j][2]); };
#pragma unroll
    for (int h = 0; h < 2; h++) {
        uint32_t p[16], a[4][4];
        c_take<1>(acc[h], p);
        if (h == 0) PROFC(1);
#pragma unroll
        for (int i = 0; i < 8; i++) {
            twiddle(p[2 * i], p[2 * i + 1], (i & 3) ^ h);
            a[(i & 3) ^ h][i >> 2] = p[2 * i];
            a[(i & 3) ^ h][2 + (i >> 2)] = p[2 * i + 1];
        }
        wgmma_fence();
        wgmma_rs_n64<0>(acc[h], a[0], desc_at(df, 4 * ps));
        wgmma_rs_n64<1>(acc[h], a[1], desc_at(df, 4 * ps + 2));
        wgmma_rs_n64<1>(acc[h], a[2], desc_at(df, 4 - 4 * ps));
        wgmma_rs_n64<1>(acc[h], a[3], desc_at(df, 6 - 4 * ps));
        wgmma_commit();
        load_w(h);
    }
    PROFC(2);
#pragma unroll
    for (int h = 0; h < 2; h++) {
        uint32_t p[16], a[4][4];
        c_take<1>(acc[h], p);
#pragma unroll
        for (int i = 0; i < 8; i++) {
            const int j = i >> 1, r = i & 1;
            if (j < 2) cmul2(p[4 * j + r], p[4 * j + 2 + r], wf[h][j][r], wf[h][j][2 + r]);
            else cmul2c(p[4 * j + r], p[4 * j + 2 + r], wf[h][j][r], wf[h][j][2 + r]);
            a[j][r] = p[4 * j + 2 + r];
            a[j][2 + r] = p[4 * j + r];
        }
        wgmma_fence();
        wgmma_rs_n64<0>(acc[h], a[0], df);
#pragma unroll
        for (int j = 1; j < 4; j++) wgmma_rs_n64<1>(acc[h], a[j], df + 2 * j);
        wgmma_commit();
    }
    PROFC(3);
#pragma unroll
    for (int j = 0; j < 12; j++) tw[4 + j / 3][j % 3] = ps ? tw[(j / 3) ^ 2][j % 3] : tw[j / 3][j % 3];
    uint32_t p[16];
    auto put = [&](int h) {
#pragma unroll
        for (int i = 0; i < 8; i++) twiddle(p[4 * (i >> 1) + (i & 1)], p[4 * (i >> 1) + 2 + (i & 1)], 4 + (i >> 1));
        if (!h) {
#pragma unroll
            for (int i = 0; i < 16; i++) asm volatile("" : "+r"(p[i]) :: "memory");
            asm volatile("bar.sync %0, 128;" :: "r"(bar) : "memory");
        }
#pragma unroll
        for (int j = 0; j < 4; j++) stsm_x4((xa ^ (j << 4)) + h * 2048, p[4 * j], p[4 * j + 1], p[4 * j + 2], p[4 * j + 3]);
        if (h && ps && !(FPOS & 2)) fence_proxy_async_smem();
    };
    c_take<1>(acc[0], p);
    put(0);
    c_take<0>(acc[1], p);
    if (!ps) put(1);
    else {
        float fin[2][64];
        auto cols = [&](int n) {
            wgmma_fence();
            wgmma_n128_set(fin[n], df, make_desc(OFF_U + n * 16384, 2048, 1024));
#pragma unroll
            for (int s = 1; s < 4; s++) wgmma_n128<0, 1>(fin[n], df + 2 * s, make_desc(OFF_U + n * 16384, 2048, 1024) + 256 * s, 1);
            wgmma_commit();
            sched_fence();
        };
        cols(0);
#pragma unroll
        for (int i = 0; i < 16; i++) asm volatile("" : "+r"(p[i]) :: "memory");
        put(1);
        PROFC(4);
#pragma unroll
        for (int n = 0; n < 2; n++) {
            wgmma_wait_all(fin[n]);
            asm volatile("bar.sync 6, 128;" ::: "memory");
            if (!n && (FPOS & 2)) fence_proxy_async_smem();
            if (!n) cols(1);
#pragma unroll
            for (int i = 0; i < 8; i++) {
                const int r = i >> 1;
                const float* a = fin[n] + 8 * i;
                stsm_x4((oa ^ ((r ^ (2 * (i & 1))) << 4)) + r * 128 + (n - 1) * 16384, pack2(a[0], a[1]), pack2(a[2], a[3]), pack2(a[4], a[5]), pack2(a[6], a[7]));
            }
        }
        if (!(FPOS & 4)) fence_proxy_async_smem();
        asm volatile("bar.sync 6, 128;" ::: "memory");
        if (FPOS & 4) fence_proxy_async_smem();
    }
    PROFC(5);
}

#define P_T 100
#define P_C 300
#define PACE_HA 100
#define PACE_HB 0
#define HN 4
#define PACE_V 100
#define VFIRST 4
#define K_XE 60
#define PACE_H 200
#define T_W0 2000
#define T_XS 2000
#define D_XS 0
#define P_XS 500
#define T_G 0
#define T_BA 1000
#define T_W1 3000
#define P_W 0
#define P_XE 600
#define P_R0 0
#define P_CAR 300
#define HWZ 2
#define R_REL 1
#define R_MID 4
#define W_EARLY 0
#define SEP 0
#define UN 1
#define FA0 16
#define P_CARB 200
#define D_CAR 20
#define HPOLL 1
#define P_HP 0
#define HS0 3
#define T_B2 4000
#define T_W 5000
#define PACE_U 200
#define PACE_L 0
#define T_FA 0
#define REG_M 216
#define REG_H 72
#define NS 4
#define QM1 42
#define QM2 36
#define SLOT_OF(k) (((k) + 1) % 4)
DEVI void tma_prefetch_4d(const CUtensorMap* map, int c0, int c1, int c2, int c3) {
    asm volatile("cp.async.bulk.prefetch.tensor.4d.L2.global [%0, {%1, %2, %3, %4}];" :: "l"(map), "r"(c0), "r"(c1), "r"(c2), "r"(c3) : "memory");
}
DEVI void bar_sync(int id, int n) { asm volatile("bar.sync %0, %1;" :: "r"(id), "r"(n) : "memory"); }
DEVI void bar_arrive(int id, int n) { asm volatile("bar.arrive %0, %1;" :: "r"(id), "r"(n) : "memory"); }
DEVI uint4 ldg128(const void* p) { uint4 v; asm volatile("ld.global.nc.v4.u32 {%0, %1, %2, %3}, [%4];" : "=r"(v.x), "=r"(v.y), "=r"(v.z), "=r"(v.w) : "l"(p)); return v; }
DEVI uint32_t ldg16(const void* p) { uint32_t v; asm volatile("ld.global.nc.u16 %0, [%1];" : "=r"(v) : "l"(p)); return v; }
DEVI uint32_t bf_fma2(uint32_t a, uint32_t b, uint32_t c) { uint32_t d; asm("fma.rn.bf16x2 %0, %1, %2, %3;" : "=r"(d) : "r"(a), "r"(b), "r"(c)); return d; }
DEVI uint32_t lo2(uint32_t a) { uint32_t d; asm("{\n.reg .b16 l, h;\nmov.b32 {l, h}, %1;\nmov.b32 %0, {l, l};\n}" : "=r"(d) : "r"(a)); return d; }
DEVI uint32_t hi2(uint32_t a) { uint32_t d; asm("{\n.reg .b16 l, h;\nmov.b32 {l, h}, %1;\nmov.b32 %0, {h, h};\n}" : "=r"(d) : "r"(a)); return d; }
DEVI void bulk_wait_read() { asm volatile("cp.async.bulk.wait_group.read 0;" ::: "memory"); }

DEVI float lds32f(uint32_t a) { float v; asm volatile("ld.shared.f32 %0, [%1];" : "=f"(v) : "r"(a) : "memory"); return v; }
DEVI uint32_t mbar_test(uint32_t bar, uint32_t parity) {
    uint32_t ok;
    asm volatile("{\n.reg .pred p;\nmbarrier.test_wait.parity.shared::cta.b64 p, [%1], %2;\nselp.u32 %0, 1, 0, p;\n}" : "=r"(ok) : "r"(bar), "r"(parity) : "memory");
    return ok;
}
template<int TA> DEVI void ring_steps(float (&acc)[2][64], uint32_t sb, uint32_t fb, int n, int ns, int s, uint32_t ph, int first_bar, int last_bar, int pi) {
    const uint64_t da0 = TA ? make_desc(0, 2048, 256, 3) : make_desc(0, 16, 1024), db0 = make_desc(16384, 16, 1024);
    const uint32_t fe = fb + 8 * ns, de = sb + OFF_BAR + 8 * BAR_EMPTY - fb;
    uint32_t eb = sb + OFF_BAR + 8 * BAR_HR, f = fb + 8 * s;
    uint64_t da = da0 + (uint32_t)(s * 2048), db = db0 + (uint32_t)(s * 2048);
    bool first = true;
    if (TA) PROFT(72);
    mbar_wait(f, ph);
    if (TA) PROFT(73);
    if (first_bar) bar_sync(first_bar, 256);
    if (TA) PROFT(74);
#pragma unroll 1
    for (;;) {
        PROFK(pi++);
        wgmma_fence();
        constexpr int QM = TA ? QM2 : QM1;
#pragma unroll
        for (int j = 0; j < 8; j++) {
            wgmma_n128<TA, 0>(acc[j & 1], da + 512 * (j & 1) + (TA ? 32 : 2) * (j >> 1), db + 2 * (j >> 1), j > 1 || !first);
            if ((QM >> j) & 1) {
                wgmma_commit();
                wgmma_wait<1>();
                if (!(QM & ((1 << j) - 1))) warp_arrive(eb);
                wgmma_fence();
            }
        }
        wgmma_commit();
        first = false;
        --n;
        if (TA && n == 0) break;
        eb = f + de;
        f += 8; da += 2048; db += 2048;
        if (f == fe) { f = fb; da = da0; db = db0; ph ^= 1; }
        const uint32_t ok = mbar_test(f, ph);
        wgmma_wait<1>();
        if (!ok) mbar_wait(f, ph);
        __syncwarp();
        if (!TA && n == 1) break;
    }
    if (!TA) {
        PROFK(pi++);
        wgmma_fence();
#pragma unroll
        for (int j = 0; j < 8; j++) {
            wgmma_n128<TA, 0>(acc[j >> 2], da + 512 * (j >> 2) + 2 * (j & 3), db + 2 * (j & 3), 1);
            if (j == 3) {
                wgmma_commit();
                wgmma_wait<1>();
                warp_arrive(eb);
                wgmma_fence();
            }
        }
        wgmma_commit();
    }
    if (last_bar) bar_arrive(last_bar, 256);
}

__global__ void __cluster_dims__(2, 1, 1) __launch_bounds__(384, 1)
fused_kernel(const __grid_constant__ CUtensorMap mapB, const __grid_constant__ CUtensorMap mapX,
             const __grid_constant__ CUtensorMap mapXs, const __grid_constant__ CUtensorMap mapU0,
             const __grid_constant__ CUtensorMap mapU2, const __grid_constant__ CUtensorMap mapXe,
             const __grid_constant__ CUtensorMap mapCre, const __grid_constant__ CUtensorMap mapCim,
             const __grid_constant__ CUtensorMap mapV, const __grid_constant__ CUtensorMap mapO,
             const __grid_constant__ CUtensorMap mapWr, const __grid_constant__ CUtensorMap mapWi,
             const __grid_constant__ CUtensorMap mapH,
             const __grid_constant__ Params P) {
    extern __shared__ __align__(1024) uint8_t sm[];
    const uint32_t sb = smem_u32(sm);
    const uint32_t bars = sb + OFF_BAR;
    const unsigned cl = blockIdx.x >> 1;
    const int role = cl < 4 ? 32 + 8 * cl : cl < 36 ? ((cl - 4) & 24) + ((cl - 5) & 7) : cl < 64 ? 33 + (cl - 36) / 7 * 8 + (cl - 30) % 7 : cl;
    const int b = role * 2 + (blockIdx.x & 1), tid = threadIdx.x, warp = __shfl_sync(0xffffffffu, tid >> 5, 0), lane = tid & 31;
    const bool main_cta = b < 128;
    if (b == 129) return;
    const int rp = (b >> 1) & 3, mq = ((b >> 3) & 2) + (b & 1), dt = ((b >> 1) & 4) + (b >> 5), tc = 4 * rp + mq;
    const int cls = b == 128 ? 128 : (b & 31) ? (b & 31) + 64 * (b >> 5) : (b == 64 ? 32 : b == 32 ? 64 : b);
    if (warp != 8 && elect()) {
        if (warp == 11) PROFG(0);
        const int u = warp - (warp > 8);
        if ((sb & 0x3FFFF) != SB0) __trap();
        asm volatile("prefetch.tensormap [%0];" :: "l"(&mapB + 2 + u) : "memory");
        mbar_init(bars + 8 * (5 + u), 1);
        if (!u) mbar_arrive(bars + 8 * (BAR_FULL + 5));
        if (u == 8) sts32(sb + OFF_KEPT + 32, 0);
        mbar_init(bars + 8 * (16 + u), u ? 4 : 1);
        mbar_init(bars + 8 * (27 + u), u < 1 ? 4 : u == 6 ? 8 : (u == 7 || u == 8) ? 64 : 1);
        fence_barrier_init();
        fence_proxy_async_smem();
    }
    __syncwarp();
    const bool real_cls = (cls & 127) == 0;
    const int t = tid & 127;
    auto load_epoch = [&]() {
        unsigned e;
        asm volatile("ld.relaxed.gpu.global.u32 %0, [%1];" : "=r"(e) : "l"(&g_cnt[CNT_EPOCH * CS]));
        return e + 1;
    };
    const int g = lane >> 2, q = lane & 3;

    if (warp < 8) {
        reg_alloc<REG_M>();
        const int wg = warp >> 2, w = warp & 3;
        if (tid == 0) PROFX(94);
        bar_sync(0, 384);
        if (tid == 224) PROFG(8);
        auto kept = [&](int i) { uint64_t v; asm volatile("ld.volatile.shared.u64 %0, [%1];" : "=l"(v) : "r"(sb + OFF_KEPT + 8 * i) : "memory"); return v; };
        const uint32_t fb = bars + 8 * (BAR_FULL + 5 * wg);
        if (wg) {
            uint32_t fa[16][4];
            auto load_fa = [&](int i0, int i1) {
#pragma unroll
                for (int i = i0; i < i1; i++)
                    asm volatile("ld.global.nc.L1::no_allocate.v4.u32 {%0, %1, %2, %3}, [%4];" : "=r"(fa[i][0]), "=r"(fa[i][1]), "=r"(fa[i][2]), "=r"(fa[i][3]) : "l"((const uint4*)c_tab + i * 128 + t));
            };
            {
                const int pp = (dt * 64 + 8 * (t & 64) + (t & 63)) & 1023;
                const uint32_t lr_ = ldg16(P.lam_re + pp), li_ = ldg16(P.lam_im + pp), ld_ = ldg16(P.log_dt + pp);
                const unsigned epoch = load_epoch();
                if (T_FA) pause(T_FA);
                load_fa(0, FA0);
                if (t < 64 && main_cta) g_agg[rp * 2048 + (dt + (t >> 5) * 8) * 128 + lane * 4 + mq] = make_uint4(0u, 0u, 0u, 0u);
                if (t < 4) asm volatile("st.shared.u64 [%0], %1;" :: "r"(sb + OFF_KEPT + 8 * lane),
                    "l"(lane == 0 ? (P.swapB ? 0xffffffffull : 0xffffff7full) | ((uint64_t)epoch << 32) : lane == 1 ? (uint64_t)g_agg : (uint64_t)&mapB) : "memory");
                const float lr = bf_lo(lr_), li = bf_lo(li_);
                const float dl = bf_round(expf(bf_lo(ld_)));
                const float mag = expf(dl * lr);
                float sn, cs; sincospif(dl * li * 0.31830988618379067f, &sn, &cs);
                const float2 l1 = make_float2(mag * cs, mag * sn);
                const float inv = 1.f / (lr * lr + li * li);
                const float2 cf = cmul(make_float2(l1.x - 1.f, l1.y), make_float2(lr * inv, -li * inv));
                sts128u(sb + OFF_K + 16 * t, __float_as_uint(l1.x), __float_as_uint(P.swapB ? -l1.y : l1.y),
                        P.swapB ? pack2(-cf.y, cf.x) : pack2(cf.x, -cf.y), P.swapB ? pack2(-cf.x, -cf.y) : pack2(-cf.y, -cf.x));
                if (tid == 128) PROFX(92);
            }
            {
                const int kk = (t >> 3) & 7, r = t & 7;
                float sn, cs;
                sincospif((float)(((cls + 256 * kk) * r) & 2047) * (1.f / 1024.f), &sn, &cs);
                sn *= 1.f / 1024.f; cs *= 1.f / 1024.f;
                const uint32_t gf = sb + OFF_G + kk * 16 + r * 2, gi = sb + OFF_G + 512 + r * 16 + (kk & 1) * 128 + (kk & 6);
                if (t < 64) {
                    sts16(gf, cs); sts16(gf + 128, real_cls ? 0.f : sn); sts16(gf + 256, -sn); sts16(gf + 384, real_cls ? 0.f : cs);
                    sts16(gi, cs); sts16(gi + 8, -sn); sts16(gi + 256, sn); sts16(gi + 264, cs);
                }
            }
            if (main_cta) {
                load_fa(FA0, 16);
                if (t == 0) PROFX(91);
                const uint32_t ua = sb + OFF_U + (lane >> 4) * 4096 + (8 * w + (lane & 7)) * 128 + ((((lane >> 3) & 1) ^ (lane & 7)) << 4);
                float acc[4][32];
                const uint64_t db = make_desc(OFF_U, 8192, 1024);
                uint32_t x[4][8], y[4][8];
                float gp[4][4];
#pragma unroll
                for (int m = 0; m < 6; m++) {
                    if (m >= 2) {
                        const int n = m - 2;
                        if (m < 5) wgmma_wait<1>(); else wgmma_wait<0>();
#pragma unroll
                        for (int i = 0; i < 32; i++) asm volatile("" : "+f"(acc[n][i]) :: "memory");
                        asm volatile("" : "+f"(gp[n][0]), "+f"(gp[n][2]) :: "memory");
#pragma unroll
                        for (int j = 0; j < 8; j++) { x[n][j] = pack2(acc[n][4 * j], acc[n][4 * j + 1]); y[n][j] = pack2(acc[n][4 * j + 2], acc[n][4 * j + 3]); }
                    }
                    if (m < 4) {
                        mbar_wait(bars + 8 * (BAR_XC + m), 0);
                        if (t == 0 && m == 3) PROF(8);
                        wgmma_fence();
                        wgmma_rs_n64<0, 1>(acc[m], fa[4 * m], db + 512 * m);
#pragma unroll
                        for (int j = 1; j < 4; j++) wgmma_rs_n64<1, 1>(acc[m], fa[4 * m + j], db + 512 * m + 128 * j);
#pragma unroll
                        for (int j = 0; j < 4; j++) wgmma_n8(gp[m], make_desc(OFF_U, 16, 1024) + 512 * m + 2 * j, make_desc(OFF_GW, 16, 1024) + 2 * j, j);
                        wgmma_commit();
                    }
                }
                if (t < 4) {
#pragma unroll
                    for (int j = 0; j < 8; j++) {
                        const uint32_t s0 = bf_add2(x[0][j], x[2][j]), s2 = bf_add2(x[1][j], x[3][j]), ty = bf_sub2(y[1][j], y[3][j]), sy = bf_add2(y[1][j], y[3][j]);
                        const uint32_t b0 = y[0][j], b2 = y[2][j];
                        y[1][j] = bf_sub2(x[3][j], x[1][j]); x[1][j] = bf_sub2(x[0][j], x[2][j]);
                        x[0][j] = bf_add2(s0, s2); y[0][j] = bf_sub2(s0, s2);
                        x[2][j] = bf_add2(b0, ty); y[2][j] = bf_add2(sy, b2) ^ 0x80008000u;
                        x[3][j] = bf_sub2(b0, ty); y[3][j] = bf_sub2(b2, sy);
                    }
                } else {
#pragma unroll
                    for (int j = 0; j < 8; j++) {
                        const uint32_t s0x = bf_add2(x[0][j], x[2][j]), s1x = bf_sub2(x[0][j], x[2][j]), s2x = bf_add2(x[1][j], x[3][j]), tx = bf_sub2(x[1][j], x[3][j]);
                        const uint32_t s0y = bf_add2(y[0][j], y[2][j]), s1y = bf_sub2(y[0][j], y[2][j]), s2y = bf_add2(y[1][j], y[3][j]), ty = bf_sub2(y[1][j], y[3][j]);
                        x[0][j] = bf_add2(s0x, s2x); y[0][j] = bf_add2(s0y, s2y);
                        x[1][j] = bf_add2(s1x, ty); y[1][j] = bf_sub2(s1y, tx);
                        x[2][j] = bf_sub2(s0x, s2x); y[2][j] = bf_sub2(s0y, s2y);
                        x[3][j] = bf_sub2(s1x, ty); y[3][j] = bf_add2(s1y, tx);
                    }
                }
                helper_sync();
                if (q == 0) {
#pragma unroll
                    for (int i = 0; i < 2; i++)
                        sts128u(sb + OFF_GW + (16 * w + 8 * i + g) * 16, __float_as_uint(gp[0][2 * i]), __float_as_uint(gp[1][2 * i]), __float_as_uint(gp[2][2 * i]), __float_as_uint(gp[3][2 * i]));
                }
#pragma unroll
                for (int c = 0; c < 4; c++)
#pragma unroll
                    for (int j = 0; j < 8; j += 2) stsm_x4((ua ^ (j << 4)) + c * 8192, x[c][j], x[c][j + 1], y[c][j], y[c][j + 1]);
                if (t == 0) PROF(21);
            }
            __syncwarp();
            warp_arrive(bars + 8 * BAR_S1);
        }
        {
            float acc[2][64];
            float2 lam8[2], lam32[2], lam64[2], l32q[2], ex[2];
            float2 ag[2][4];
            if (main_cta) {
                ring_steps<0>(acc, sb, fb, 16, 5 - wg, wg * SLOT_OF(16), 0, 2 * wg, 2 + wg, 16 * wg);
                mbar_wait(bars + 8 * BAR_S1, 0);
                const uint4* ap = (const uint4*)kept(1) + (((tc - 1 - q) >> 2) * 2048 + (dt + 8 * wg) * 128 + t);
                const uint64_t k0 = kept(0);
                const uint32_t fl = (uint32_t)k0;
                uint32_t tag = ((uint32_t)(k0 >> 32) & 7) | 8;
                float2 lam1[2], la[2], lb[2], l2[2], l4[2], wq[2], w4[2];
                uint32_t m0[2], m1[2], kr[8], ki[8];
                auto weights = [&](int i) {
                    const float2 l128 = csq(lam64[i]), l256 = csq(l128), one = make_float2(1.f, 0.f);
                    w4[i] = csq(l256);
                    wq[i] = cmul(((tc - 1 - q) & 1) ? l128 : one, ((tc - 1 - q) & 2) ? l256 : one);
                    l32q[i] = cmul((q & 1) ? la[i] : one, (q & 2) ? lb[i] : one);
                    asm volatile("" : "+f"(w4[i].x), "+f"(w4[i].y), "+f"(wq[i].x), "+f"(wq[i].y), "+f"(l32q[i].x), "+f"(l32q[i].y));
                };
#pragma unroll
                for (int i = 0; i < 2; i++) {
                    const uint4 kv = lds128u(sb + OFF_K + (64 * wg + 32 * i + (t >> 2)) * 16);
                    lam1[i] = make_float2(__uint_as_float(kv.x), __uint_as_float(kv.y));
                    m0[i] = kv.z; m1[i] = kv.w;
                    l2[i] = csq(lam1[i]); l4[i] = csq(l2[i]); lam8[i] = csq(l4[i]);
                    lam32[i] = csq(csq(lam8[i])); lam64[i] = csq(lam32[i]);
                    la[i] = q >= 1 ? lam32[i] : make_float2(0.f, 0.f); lb[i] = q >= 2 ? lam64[i] : make_float2(0.f, 0.f);
                    asm volatile("" : "+f"(lam8[i].x), "+f"(lam8[i].y), "+f"(la[i].x), "+f"(la[i].y), "+f"(lb[i].x), "+f"(lb[i].y), "+f"(lam64[i].x), "+f"(lam64[i].y));
                    if (W_EARLY) weights(i);
                }
                kr[1] = pack2(l2[0].x, l2[1].x); ki[1] = pack2(l2[0].y, l2[1].y); kr[3] = pack2(l4[0].x, l4[1].x); ki[3] = pack2(l4[0].y, l4[1].y);
                asm volatile("" : "+r"(kr[1]), "+r"(ki[1]), "+r"(kr[3]), "+r"(ki[3]));
                uint32_t pub = q == 3 && tc < 15;
                const uint4* as = ap + (2045 + mq);
                asm volatile("" : "+l"(ap), "+l"(as), "+r"(tag), "+r"(pub));
                sched_fence();
                float2 v[2];
                wgmma_wait<1>();
#pragma unroll
                for (int o = 0; o < 64; o++) asm volatile("" : "+f"(acc[0][o]) :: "memory");
#pragma unroll
                for (int i = 0; i < 2; i++) {
#pragma unroll
                    for (int r = 1; r < 8; r++) {
#pragma unroll
                        for (int c = 0; c < 4; c++) {
                            const int o = 16 * c + 4 * (r >> 1) + (r & 1), u = 16 * c + 4 * ((r - 1) >> 1) + ((r - 1) & 1);
                            const float2 n = cfma(lam1[i], make_float2(acc[i][u], acc[i][u + 2]), make_float2(acc[i][o], acc[i][o + 2]));
                            acc[i][o] = n.x; acc[i][o + 2] = n.y;
                        }
                        if (!i && r == R_REL) {
#pragma unroll
                            for (int o = 0; o < 64; o++) asm volatile("" : "+f"(acc[0][o]));
                            sched_fence();
                            wgmma_wait_all(acc[1]);
                            warp_arrive(bars + 8 * (BAR_EMPTY + SLOT_OF(15)));
                            sched_fence();
                            if (tid == 0) PROF(3);
                            if (tid == 128) PROF(25);
                            if (tid == 224) PROFG(12);
                        }
                        if (i && r == R_MID) {
#pragma unroll
                            for (int o = 0; o < 64; o++) asm volatile("" : "+f"(acc[1][o]));
                            asm volatile("" : "+f"(v[0].x), "+f"(v[0].y));
                            sched_fence();
                        }
                    }
#pragma unroll
                    for (int c = 0; c < 4; c++) ag[i][c] = make_float2(acc[i][16 * c + 13], acc[i][16 * c + 15]);
                    v[i] = ag[i][0];
#pragma unroll
                    for (int c = 1; c < 4; c++) v[i] = cfma(lam8[i], v[i], ag[i][c]);
                    float2 n = make_float2(__shfl_up_sync(0xffffffffu, v[i].x, 1, 4), __shfl_up_sync(0xffffffffu, v[i].y, 1, 4));
                    v[i] = cfma(la[i], n, v[i]);
                    n = make_float2(__shfl_up_sync(0xffffffffu, v[i].x, 2, 4), __shfl_up_sync(0xffffffffu, v[i].y, 2, 4));
                    v[i] = cfma(lb[i], n, v[i]);
                }
                asm volatile("{\n.reg .b64 a, b;\n.reg .pred p;\nsetp.ne.u32 p, %5, 0;\nmov.b64 a, {%1, %2};\nmov.b64 b, {%3, %4};\n@p st.relaxed.gpu.global.v2.b64 [%0], {a, b};\n}"
                    :: "l"(as), "r"((__float_as_uint(v[0].x) & ~15u) | tag), "r"(__float_as_uint(v[0].y)),
                       "r"((__float_as_uint(v[1].x) & ~15u) | tag), "r"(__float_as_uint(v[1].y)), "r"(pub) : "memory");
                PROFS(72 + 8 * wg);
                sched_fence();
                uint4 rr[4];
                auto poll = [&]() {
#pragma unroll
                    for (int n = 0; n < 4; n++)
                        asm volatile("{\n.reg .b64 a, b;\n.reg .pred p;\nsetp.lt.s32 p, %5, %6;\ncvt.u64.u32 a, %7;\nmov.b64 b, a;\n"
                                     "@p ld.relaxed.gpu.global.v2.b64 {a, b}, [%4];\nmov.b64 {%0, %1}, a;\nmov.b64 {%2, %3}, b;\n}"
                            : "=r"(rr[n].x), "=r"(rr[n].y), "=r"(rr[n].z), "=r"(rr[n].w) : "l"(ap - 2048 * n), "r"(4 * n), "r"(tc - q), "r"(tag) : "memory");
                };
                uint32_t hp[2][32];
                auto scale = [&](int i, uint32_t& x, uint32_t& y) {
                    const uint32_t u = bf_fma2(lo2(m0[i]), x, bf_mul2(hi2(m0[i]), y));
                    y = bf_fma2(lo2(m1[i]), x, bf_mul2(hi2(m1[i]), y)); x = u;
                };
#pragma unroll
                for (int i = 0; i < 2; i++) {
                    ex[i] = make_float2(__shfl_up_sync(0xffffffffu, v[i].x, 1, 4), __shfl_up_sync(0xffffffffu, v[i].y, 1, 4));
#pragma unroll
                    for (int j = 0; j < 16; j++) {
                        const int o = 4 * (j >> 2) + 16 * (j & 1) + ((j >> 1) & 1), u = 8 * (j >> 2) + (j & 3);
                        hp[i][u] = pack2(acc[i][o], acc[i][o + 32]); hp[i][u + 4] = pack2(acc[i][o + 2], acc[i][o + 34]);
                    }
                    if (q == 0) ex[i] = make_float2(0.f, 0.f);
                }
                if (SEP) {
#pragma unroll
                    for (int j = 0; j < 64; j++) asm volatile("" : "+r"(hp[j >> 5][j & 31]));
                    sched_fence();
                }
#pragma unroll
                for (int j = 0; j < 32; j++) scale(j >> 4, hp[j >> 4][2 * (j & 12) + (j & 3)], hp[j >> 4][2 * (j & 12) + (j & 3) + 4]);
#pragma unroll
                for (int i = 0; i < 2; i++) {
#pragma unroll
                    for (int j = 0; j < 32; j++) asm volatile("" : "+r"(hp[i][j]));
                    asm volatile("" : "+f"(ex[i].x), "+f"(ex[i].y));
                }
                PROFS(73 + 8 * wg);
                mbar_wait(bars + 8 * (wg ? BAR_HD : BAR_EMPTY + 4), 0);
                if (wg) mbar_wait(bars + 8 * BAR_WR, 0);
                pause((wg ? P_CARB : P_CAR) + D_CAR * tc);
                poll();
                sched_fence();
                uint32_t hs = sb + OFF_HS + (lane >> 4) * 1024 + w * 256 + (lane & 7) * 32 + (((lane << 1) ^ (lane << 2)) & 16), hs1 = hs + 16384 + wg * 18432;
                asm volatile("" : "+r"(hs), "+r"(hs1));
                {
                    const uint32_t cj = (fl & 128) ? 0u : 0x80008000u;
                    kr[0] = pack2(lam1[0].x, lam1[1].x); ki[0] = pack2(lam1[0].y, lam1[1].y) ^ cj; kr[7] = pack2(lam8[0].x, lam8[1].x); ki[7] = pack2(lam8[0].y, lam8[1].y) ^ cj;
                    ki[1] ^= cj; ki[3] ^= cj;
                    kr[2] = kr[1]; ki[2] = ki[1]; cmul2(kr[2], ki[2], kr[0], ki[0]);
                    const uint32_t n4 = neg2(ki[3]);
#pragma unroll
                    for (int j = 0; j < 3; j++) { kr[4 + j] = kr[j]; ki[4 + j] = ki[j]; cmul2(kr[4 + j], ki[4 + j], kr[3], ki[3], n4); }
#pragma unroll
                    for (int j = 0; j < 8; j++) asm volatile("" : "+r"(kr[j]), "+r"(ki[j]));
                    if (!W_EARLY) { weights(0); weights(1); }
                }
                sched_fence();
                float2 pt[2];
                auto sum = [&]() {
                    uint32_t bad = 0;
#pragma unroll
                    for (int j = 0; j < 4; j++) bad |= (rr[j].x ^ tag) | (rr[j].z ^ tag);
#pragma unroll
                    for (int i = 0; i < 2; i++) {
                        auto val = [&](int n) { return make_float2(__uint_as_float(i ? rr[n].z : rr[n].x), __uint_as_float(i ? rr[n].w : rr[n].y)); };
                        pt[i] = cmul(wq[i], cfma(w4[i], cfma(w4[i], cfma(w4[i], val(3), val(2)), val(1)), val(0)));
                        asm volatile("" : "+f"(pt[i].x), "+f"(pt[i].y));
                    }
                    return __any_sync(0xffffffffu, bad & 15);
                };
                if (sum()) {
#pragma unroll 1
                    for (unsigned n = 0; n < SPIN_LIMIT; n++) {
                        if (n < 3) PROFS(74 + 8 * wg + n);
                        poll();
                        if (!sum()) break;
                    }
                }
#pragma unroll
                for (int i = 0; i < 2; i++) {
                    float2 part = pt[i];
                    part.x += __shfl_xor_sync(0xffffffffu, part.x, 1); part.y += __shfl_xor_sync(0xffffffffu, part.y, 1);
                    part.x += __shfl_xor_sync(0xffffffffu, part.x, 2); part.y += __shfl_xor_sync(0xffffffffu, part.y, 2);
                    ex[i] = cfma(l32q[i], part, ex[i]);
#pragma unroll
                    for (int c = 0; c < 4; c++) { const float2 e = cfma(lam8[i], ex[i], ag[i][c]); ag[i][c] = ex[i]; ex[i] = e; }
                }
                if (t == 0) PROF(4 + 25 * wg);
#pragma unroll
                for (int i = 0; i < 2; i++) {
                    uint32_t cr[2], ci[2], cn[2];
#pragma unroll
                    for (int c = 0; c < 2; c++) { cr[c] = pack2(ag[i][c].x, ag[i][c + 2].x); ci[c] = pack2(ag[i][c].y, ag[i][c + 2].y); scale(i, cr[c], ci[c]); cn[c] = ci[c] ^ 0x80008000u; }
#pragma unroll
                    for (int n = 0; n < 4; n++) {
                        uint32_t* h = &hp[i][16 * (n & 1) + 4 * (n >> 1)];
                        if (fl & (256 << (4 * i + n))) {
#pragma unroll
                            for (int j = 0; j < 8; j++) {
                                const uint32_t x = kr[4 * (n & 1) + (j >> 1)], y = ki[4 * (n & 1) + (j >> 1)];
                                uint32_t& d = h[j + (j & 4)];
                                d = bf_fma2(i ? hi2(x) : lo2(x), (n & 2) ? ci[j & 1] : cr[j & 1], bf_fma2(i ? hi2(y) : lo2(y), (n & 2) ? cr[j & 1] : cn[j & 1], d));
                            }
                        }
                        stsm_x4((i ? hs1 : hs) + n * 4096, h[0], h[1], h[2], h[3]);
                        stsm_x4((i ? hs1 : hs) + n * 4096 + 2048, h[8], h[9], h[10], h[11]);
                        if (4 * i + n == HS0 - 1 || 4 * i + n == 7) {
                            if (4 * i + n == 7 || HF) fence_proxy_async_smem();
                            __syncwarp();
                            warp_arrive(bars + 8 * (BAR_HW + (4 * i + n == 7)));
                        }
                        if (!i && !n && !wg) PROFS(77);
                    }
                }
                if (t == 0) PROF(5 + 25 * wg);
            } else {
                mbar_wait(bars + 8 * BAR_S1, 0);
            }
        }
        if (!main_cta) {
            if (wg) mbar_wait(bars + 8 * BAR_WR, 0);
            fence_proxy_async_smem();
        }
#pragma unroll 1
        for (int ps = wg; ps < 1 + 2 * wg; ps++) {
            if (ps != 1) {
                if (!ps) mbar_wait(bars + 8 * BAR_U, 0);
                if (t == 0) PROF(ps ? 7 : 23);
                radix8(sb, ps, w, lane, 5 + wg);
                if (t == 0) PROF(ps ? 24 : 22);
                if (ps) break;
                bar_sync(5, 128);
                if (FPOS & 1) fence_proxy_async_smem();
            }
            mbar_wait(bars + 8 * (BAR_C + ps), 0);
            phase_c(sb, ps, b + ps == 0, w, lane);
        }
        if (wg == 0) {
            __syncwarp();
            warp_arrive(bars + 8 * BAR_WR);
            if (main_cta) {
                float acc[2][64];
                ring_steps<1>(acc, sb, bars + 8 * BAR_FULL, 31, NS, SLOT_OF(32), 1, 3, 0, 32);
                auto full = [&](int k) { mbar_wait(bars + 8 * (BAR_FULL + SLOT_OF(k)), 1); PROFT(k); };
                auto hstep = [&](int k, int i) {
                    const uint64_t da = make_desc(SLOT_OF(k) * SLOT + i * 8192, 2048, 256, 3), db = make_desc(SLOT_OF(k) * SLOT + 16384, 16, 1024);
                    wgmma_fence();
#pragma unroll
                    for (int j = 0; j < 4; j++) wgmma_n128<1, 0>(acc[i], da + 32 * j, db + 2 * j, 1);
                };
                auto vstep = [&](int k, int i) {
                    const uint64_t da = make_desc(OFF_U - i * 32768 + k * 8192, 16, 1024), db = make_desc(SLOT_OF(64 + (k >> 1)) * SLOT + (k & 1) * 16384, 8192, 1024);
                    if (k || !i) wgmma_fence();
#pragma unroll
                    for (int j = 0; j < 4; j++) wgmma_n128<0, 1>(acc[i], da + 2 * j, db + 128 * j, 1);
                };
                __syncwarp();
                full(63);
                hstep(63, 0);
                bar_sync(4, 256);
                full(64);
                vstep(0, 0);
                vstep(1, 0);
                const CUtensorMap* maps = (const CUtensorMap*)kept(3);
                const uint32_t ob = sb + OFF_U + w * 2048, oa = ob + g * 256 + (((q >> 1) ^ (2 * g & 6)) << 4) + (q & 1) * 8;
#pragma unroll
                for (int i = 0; i < 2; i++) {
                    uint4 e[8];
                    const uint2 sc = lds64u(sb + OFF_SC + (64 * i + 16 * w + 2 * g) * 4);
                    bar_sync(8 + i, 256);
#pragma unroll
                    for (int j = 0; j < 8; j++) e[j] = lds128u(sb + OFF_HS + i * 16384 + (j >> 2) * 8192 + w * 2048 + (j & 3) * 512 + lane * 16);
                    if (i) wgmma_wait<0>();
                    else {
                        full(65);
                        vstep(2, 0);
                        vstep(3, 0);
                        wgmma_commit();
                        hstep(63, 1);
                        vstep(0, 1);
                        wgmma_commit();
                        wgmma_wait<1>();
                    }
#pragma unroll
                    for (int o = 0; o < 64; o++) asm volatile("" : "+f"(acc[i][o]) :: "memory");
                    if (tid == 0) PROF(17 + i);
                    if (tid == 96 && i) PROFG(20);
#pragma unroll
                    for (int c = 0; c < 4; c++) {
#pragma unroll
                        for (int j = 0; j < 8; j++) {
                            const int o = 16 * c + 2 * j;
                            const uint4 e4 = e[2 * c + (j >> 2)];
                            const uint32_t ev = (j & 2) ? ((j & 1) ? e4.w : e4.z) : ((j & 1) ? e4.y : e4.x);
                            const float f = __uint_as_float((j & 1) ? sc.y : sc.x);
                            sts64((oa ^ ((j >> 1) << 5) ^ ((j & 1) * 144)) + c * 8192 - i * 32768, fmaf(f, acc[i][o], bf_lo(ev)), fmaf(f, acc[i][o + 1], bf_hi(ev)));
                        }
                        if (!i && c >= VFIRST && c < 3) {
                            vstep(c + 1, 1);
                            if (c == 2) wgmma_commit();
                        }
                        fence_proxy_async_smem();
                        __syncwarp();
                        if (elect()) tma_store_3d(maps + 9, ob + c * 8192 - i * 32768, 128 * dt + 32 * c, 128 * (tc & 1) + 64 * i + 16 * w, tc >> 1);
                        __syncwarp();
                        if (!i && c < VFIRST && c < 3) {
                            vstep(c + 1, 1);
                            if (c == 2) wgmma_commit();
                        }
                    }
                }
                if (elect()) {
                    bulk_commit();
                    bulk_wait_read();
                }
                if (tid == 0) PROF(19);
                if (tid == 96) { PROF(20); PROFG(4); }
            }
        } else {
            __syncwarp();
            if (tid == 224) PROFG(16);
            if (main_cta) {
                float gs[16];
                uint32_t dk[16], tv[4][4];
#pragma unroll
                for (int j = 0; j < 16; j++) gs[j] = __ldcg(g_gp + (16 * (tc >> 1) + j) * 256 + 128 * (tc & 1) + t);
#pragma unroll
                for (int j = 0; j < 16; j++) dk[j] = ldg32u(P.dskip + 128 * dt + 8 * j + 2 * q);
                const int m0 = ((t >> 2) & 14) + (t >> 6), c0 = 4 * ((t ^ (t >> 3)) & 7);
#pragma unroll
                for (int j = 0; j < 16; j++) {
                    const float a = (float)((j & 3) || c0 ? c0 + (j & 3) : -96) * ((float)(128 * (tc & 1) + 4 * (j & 12) + m0) * 0.024543692606170260f);
                    tv[j >> 2][j & 3] = pack2(__cosf(a), -__sinf(a));
                }
#pragma unroll
                for (int j = 0; j < 4; j++) gs[j] = (gs[j] + gs[j + 4]) + (gs[j + 8] + gs[j + 12]);
                gs[0] = (gs[0] + gs[1]) + (gs[2] + gs[3]);
                const float gg = bf_round(__fdividef(1.f, 1.f + __expf(-bf_round(gs[0])))), og = bf_round(1.f - gg), o2 = fmaxf(2.f * og, 0x1p-40f);
                sts32(sb + OFF_SC + 4 * t, __float_as_uint(o2));
                sts32(sb + OFF_SC + 512 + 4 * t, pack2(__fdividef(gg, o2), og));
                bar_sync(6, 128);
                if (t == 0) PROFX(95);
                auto sign = [](uint32_t n) { return (((n + 1) & 2) << 30) | ((n & 2) << 14); };
                const uint32_t sel = (t & 64) ? 0x1032 : 0x3210;
#pragma unroll
                for (int e = 1; e >= 0; e--) {
                    uint32_t f[4];
#pragma unroll
                    for (int j = 0; j < 4; j++) f[j] = lds16(sb + OFF_SC + 512 + (64 * e + 16 * j + m0) * 4) * 0x10001u;
                    mbar_wait(bars + 8 * (e ? BAR_HD + 1 : BAR_U), !e);
#pragma unroll
                    for (int j = 0; j < 16; j++) {
                        const int k = j & 3, r = j >> 2;
                        uint32_t o[4];
#pragma unroll
                        for (int u = 0; u < 4; u++) {
                            uint32_t v = tv[r][u];
                            if (u == 0 && k < 2 && !c0) v = k ? 0x3f80u : 0x3f003f00u | (t & 64) << 25;
                            if (e) v = ((u & 1) ? __byte_perm(v, 0, 0x1032) : v) ^ sign(u);
                            o[u] = bf_mul2((k & 1) ? __byte_perm(v, 0, sel) : v, f[r] ^ sign(k * m0));
                        }
                        sts128u(sb + OFF_U - e * 32768 + (4 * k + r) * 2048 + t * 16, o[0], o[1], o[2], o[3]);
                    }
                }
                fence_proxy_async_smem();
                bar_arrive(4, 256);
                if (t == 0) PROF(16);
                const uint32_t xa = sb + OFF_HS + (16 * w + (lane & 15)) * 128 + (((lane >> 4) ^ (lane & 7)) << 4);
#pragma unroll
                for (int e = 0; e < 2; e++) {
                    const uint2 u = lds64u(sb + OFF_SC + 512 + (64 * e + 16 * w + 2 * g) * 4);
                    const uint32_t o0 = __byte_perm(u.x, 0, 0x3232), o1 = __byte_perm(u.y, 0, 0x3232);
                    uint32_t x[8][4];
                    mbar_wait(bars + 8 * (BAR_W + e), 1);
#pragma unroll
                    for (int j = 0; j < 8; j++) ldsm_x4(x[j], (xa ^ ((j & 3) << 5)) + e * 16384 + (j >> 2) * 8192);
#pragma unroll
                    for (int j = 0; j < 8; j++) {
#pragma unroll
                        for (int c = 0; c < 4; c++) x[j][c] = bf_mul2(bf_mul2(x[j][c], dk[2 * j + (c >> 1)]), (c & 1) ? o1 : o0);
                        sts128u(sb + OFF_HS + e * 16384 + (j >> 2) * 8192 + w * 2048 + (j & 3) * 512 + lane * 16, x[j][0], x[j][1], x[j][2], x[j][3]);
                    }
                    bar_arrive(8 + e, 256);
                    if (t == 0 && !e) PROF(15);
                }
            }
            if (t == 0) {
                const unsigned old = atomicAdd(&g_cnt[CNT_DONE * CS], 1u);
                if (old == 128) { g_cnt[CNT_DONE * CS] = 0; g_cnt[CNT_EPOCH * CS] = (uint32_t)(kept(0) >> 32); }
            }
        }
    } else {
        reg_dealloc<REG_H>();
        const int w = warp - 8;
        if (w == 0) {
            if (elect()) {
                PROF(0);
#pragma unroll
                for (int i = 0; i < 5; i++) mbar_init(bars + 8 * i, 1);
                fence_barrier_init();
                fence_proxy_async_smem();
                PROFX(88);
            }
            __syncwarp();
            bar_arrive(0, 384);
            if (elect()) {
                if (main_cta) {
#pragma unroll 1
                    for (int k = 0; k < 5; k++) {
                        const uint32_t full = bars + 8 * (BAR_FULL + k), st = sb + k * SLOT;
                        mbar_expect_tx(full, SLOT);
                        tma_load_4d(st, &mapB, full, k * 64, 0, 0, dt * 8);
                        tma_load_4d(st + 16384, &mapX, full, k * 64, 0, 0, tc * 64);
                        if (k == 0) PROFX(89);
                        if (P_R0) pause(P_R0);
                    }
                }
                PROF(27);
            }
            __syncwarp();
            bar_sync(7, 64);
            if (!main_cta || !elect()) return;
            {
                int s = 0; uint32_t ph = 0;
#pragma unroll 1
                for (int k = 5; k < 32; k++) {
                    asm volatile(WAIT_LOOP
                        "cp.async.bulk.tensor.4d.shared::cluster.global.mbarrier::complete_tx::bytes [%3], [%5, {%7, %10, %10, %8}], [%2];\n"
                        "cp.async.bulk.tensor.4d.shared::cluster.global.mbarrier::complete_tx::bytes [%4], [%6, {%7, %10, %10, %9}], [%2];\n"
                        "mbarrier.arrive.expect_tx.shared::cta.b64 _, [%2], 32768;\n}"
                        :: "r"(bars + 8 * (BAR_EMPTY + s)), "r"(ph), "r"(bars + 8 * (BAR_FULL + s + (k >> 4) * 5)), "r"(sb + s * SLOT + 16384), "r"(sb + s * SLOT),
                           "l"(&mapX), "l"(&mapB), "r"((k & 15) * 64), "r"(tc * 64), "r"(dt * 8 + (k >> 4) * 64), "r"(0) : "memory");
                    PROFR(k < 19 ? k - 5 : k - 4);
                    if (++s == (k < 15 ? 5 : NS)) { s = 0; ph ^= 1; }
                }
                auto load_x = [&](int e) {
                    mbar_expect_tx(bars + 8 * (BAR_W + e), 16384);
#pragma unroll
                    for (int i = 0; i < 2; i++) tma_load_5d(sb + OFF_HS + e * 16384 + i * 8192, &mapXe, bars + 8 * (BAR_W + e), 128 * dt + 64 * i, 8 * (tc & 1) + 4 * e, tc >> 1);
                };
                const uint8_t* hp = g_hT + tc * 16384;
#pragma unroll 1
                for (int h = 0; h < 32; h++) {
                    asm volatile("{\n.reg .pred q;\n.reg .u32 v, m;\nld.volatile.shared.u32 v, [%10];\nsetp.gt.u32 q, v, %8;\nmov.u32 m, 0;\n" WAIT_LOOP
                        "cp.async.bulk.tensor.3d.shared::cluster.global.mbarrier::complete_tx::bytes [%3], [%5, {%9, %7, %8}], [%2];\n"
                        "@q bra LH;\nLV:\nld.volatile.shared.u32 v, [%10];\nadd.u32 m, m, 1;\nsetp.le.u32 q, v, %8;\nsetp.lt.and.u32 q, m, 4194304, q;\n@q bra LV;\nLH:\n"
                        "cp.async.bulk.shared::cluster.global.mbarrier::complete_tx::bytes [%4], [%6], 16384, [%2];\n"
                        "mbarrier.arrive.expect_tx.shared::cta.b64 _, [%2], 32768;\n}\n}"
                        :: "r"(bars + 8 * (BAR_EMPTY + s)), "r"(ph), "r"(bars + 8 * (BAR_FULL + s)), "r"(sb + s * SLOT + 16384), "r"(sb + s * SLOT),
                           "l"(&mapCre + (h & 1)), "l"(hp), "r"(dt * 128), "r"(h >> 1), "r"(0), "r"(sb + OFF_KEPT + 32) : "memory");
                    PROFR(h + 28);
                    hp += 16 * 16384;
                    if (h == K_XE - 32) load_x(0);
                    if (++s == NS) { s = 0; ph ^= 1; }
                }
                {
                        mbar_wait(bars + 8 * (BAR_F + 2), 0);
#pragma unroll
                        for (int i = 0; i < 2; i++) {
                            const uint32_t pb = bars + 8 * (BAR_XC + i), full = bars + 8 * (BAR_FULL + SLOT_OF(64 + i)), st = sb + SLOT_OF(64 + i) * SLOT;
                            uint32_t rb;
                            asm("mapa.shared::cluster.u32 %0, %1, %2;" : "=r"(rb) : "r"(pb), "r"(~b & 1));
                            asm volatile(WAIT_LOOP "mbarrier.arrive.shared::cluster.b64 _, [%2];\n}" :: "r"(bars + 8 * (BAR_EMPTY + SLOT_OF(64 + i))), "r"(ph), "r"(rb) : "memory");
                            asm volatile(WAIT_LOOP "cp.async.bulk.tensor.3d.shared::cluster.global.mbarrier::complete_tx::bytes.multicast::cluster [%2], [%3, {%5, %6, %7}], [%4], %8;\n}"
                                :: "r"(pb), "r"(1), "r"(st + (b & 1) * 16384), "l"(&mapV), "r"(full), "r"(0), "r"(i * 128 + (b & 1) * 64), "r"((tc >> 1) * 16 + dt * 2), "h"((uint16_t)3) : "memory");
                            mbar_expect_tx(full, SLOT);
                            PROFR(60 + i);
                        }
                    }
                load_x(1);
            }
        } else {
            const unsigned epoch = load_epoch();
            bar_sync(0, 384);
            if (w == 1) {
                bar_arrive(7, 64);
                if (!elect()) return;
                {
                    if (main_cta) {
                        pause(T_XS);
                        bulk_load(sb + OFF_GW, P.gate_w + (b & 15) * 64, 128, bars + 8 * BAR_XC);
#pragma unroll 1
                        for (int c = 0; c < 4; c++) {
                            mbar_expect_tx(bars + 8 * (BAR_XC + c), c ? 8192 : 8192 + 128);
                            tma_load_4d(sb + OFF_U + c * 8192, &mapXs, bars + 8 * (BAR_XC + c), (b & 15) * 64, 0, c, b >> 4);
                            pause(P_XS);
                        }
                    }
                    mbar_wait(bars + 8 * BAR_S1, 0);
                    fence_proxy_async_smem();
                    if (main_cta) {
#pragma unroll 1
                        for (int c = 0; c < 4 * UN; c++) {
                            if (c) pause(PACE_U);
                            tma_store_4d(&mapU0, sb + OFF_U + c * (8192 / UN), (b & 15) * 64, UN == 4 ? 32 * (c >> 2) + 16 * (c & 1) : 32 * (c / UN), UN == 4 ? (c >> 1) & 1 : c % UN, b >> 4);
                        }
                        bulk_store(g_gp + b * 256, sb + OFF_GW, 1024);
                        bulk_commit();
                        bulk_wait0();
                        signal_counter(&g_cnt[CNT_U * CS]);
                    }
                    PROF(9);
                    mbar_expect_tx(bars + 8 * BAR_U, 32768);
                    wait_counter(&g_cnt[CNT_U * CS + (b & (NREP - 1)) * RS], epoch * 128);
                    PROF(11);
#pragma unroll
                    for (int i = 0; i < 8; i++) {
                        if (PACE_L && i && !(i & 1)) pause(PACE_L);
                        tma_load_4d(sb + OFF_U + i * 4096, &mapU2, bars + 8 * BAR_U, 0, 0, (i & 3) * 4, b == 128 ? 1 : b == 0 ? 0 : 2 * b + (i >> 2));
                    }
                    if (main_cta) {
#pragma unroll 1
                        for (int i = 0; i < 2; i++) {
#pragma unroll 1
                            for (int j = 0; j < 2 * HN; j++) {
                                const int hf = j / HN, jj = j % HN;
                                if (j) pause(i ? PACE_HB : PACE_HA);
                                if (j == 0 || j == HS0 * HN / 4) mbar_wait(bars + 8 * (BAR_HW + (j > 0)), i);
                                if (j == 0 && !HF) fence_proxy_async_smem();
                                tma_store_3d(&mapH, sb + OFF_HS + hf * (16384 + i * 18432) + jj * (16384 / HN), 0, 2 * tc + hf, (dt + 8 * i) * 16 + jj * (16 / HN));
                            }
                            bulk_commit();
                            bulk_wait0();
#pragma unroll
                            for (int r = 0; r < NREPH; r++)
                                asm volatile("red.relaxed.gpu.global.add.u64 [%0], %1;" :: "l"(&g_cnt[(CNT_H + 2 * i + (tc >> 3)) * CS + r * RS]), "l"(1ull << (8 * dt)) : "memory");
                            mbar_arrive(bars + 8 * (BAR_HD + i));
                            PROF(i ? 6 : 26);
                            const unsigned* cp = &g_cnt[(CNT_H + 2 * i + (tc & 1)) * CS + ((b >> 1) & (NREPH - 1)) * RS];
#pragma unroll 1
                            for (unsigned n = 0; n < SPIN_LIMIT; n++) {
                                uint64_t v;
                                asm volatile("ld.relaxed.gpu.global.u64 %0, [%1];" : "=l"(v) : "l"(cp) : "memory");
                                v = epoch * 0x0808080808080808ull - v;
                                sts32(sb + OFF_KEPT + 32, (__clzll(__brevll(v)) >> 3) + 8 * i);
                                if (!v) break;
                                if (P_HP) pause(P_HP);
                            }
                            PROF(1 + i);
                        }
                    }
                }
            } else {
                const int ld = (1026 * cls) >> 7, lm = (1026 * ((256 - cls) & 255)) >> 7;
                if (elect() && main_cta) {
                    if (w == 3) {
                        pause(T_W);
#pragma unroll 1
                        for (int i = 0; i < 8; i++) {
                            tma_prefetch_4d(&mapWr + (i & 1), 0, (i & 2) ? lm : ld, i >> 2, 0);
                            pause(200);
                        }
                    } else {
                        pause(T_BA + D_XS * tc);
                        if (tc > 4) tma_prefetch_4d(&mapB, tc * 64, 0, 0, dt * 8);
                        pause(T_B2);
                        bulk_prefetch_l2(((b & 1) ? P.b_im : P.b_re) + (64 + (b >> 1)) * 8192, 16384);
                        pause(T_W0 - D_XS * tc);
                    }
                }
#pragma unroll 1
                for (int ps = 0; ps < 2; ps++) {
                    const uint32_t wb = sb + OFF_W + (1 - ps) * 18432;
                    if (w == 2 && elect()) {
                        const uint32_t bw = bars + 8 * (BAR_W + ps);
                        if (ps && main_cta) mbar_wait(bars + 8 * BAR_HD, 0);
                        mbar_expect_tx(bw, ps ? 18432 : 18432 + 8192);
#pragma unroll 1
                        for (int i = 0; i < 4; i++) {
                            tma_load_4d(wb + (i >> 1) * 4608 + (i & 1) * 9216, &mapWr + (i & 1), bw, 0, i < 2 ? ld : lm, (i < 2 || b == 0) ? ps : 1 - ps, 0);
                            pause(P_W);
                        }
                        if (!ps) bulk_load(sb + OFF_F, c_tab + 8192, 8192, bw);
                        PROFX(85 + ps);
                    }
                    if (w == 3 && ps && main_cta && elect()) {
#pragma unroll 1
                        for (int i = 0; i < 8; i++) {
                            bulk_prefetch_l2(((b & 1) ? P.c_im : P.c_re) + (size_t)(b >> 1) * 16384 + i * 2048, 4096);
                            pause(P_C);
                        }
                    }
                    __syncwarp();
                    mbar_wait(bars + 8 * (BAR_W + ps), 0);
                    if (tid == 320) PROF(ps ? 31 : 10);
#pragma unroll 1
                    for (int u = 0; u < 4; u++) {
                        const int row = 2 * (w - 2) + (u >> 1), pl = u & 1;
                        const uint32_t dp = wb + pl * 9216 + row * 1152, mp = wb + pl * 9216 + 4608 + ((b == 0 && ps == 0) ? (4 - row) & 3 : 3 - row) * 1152;
                        const uint32_t od = dp + ((1026 * cls) & 127), om = mp + ((1026 * (256 - cls)) & 127);
                        uint32_t v[4][8], o[4][4];
#pragma unroll
                        for (int i = 0; i < 8; i++) {
                            const uint4 r = lds128u((i < 4 ? (od & ~15u) + 16 * lane + (i >> 1) * 512 : ((om + 1010) & ~15u) - 16 * lane - ((i >> 1) & 1) * 512) + (i & 1) * 16);
                            uint32_t* d = &v[i >> 1][4 * (i & 1)];
                            d[0] = r.x; d[1] = r.y; d[2] = r.z; d[3] = r.w;
                        }
                        const uint32_t e0 = lds16(om), e1 = lds16(od + 1024);
                        auto fwd = [&](int ws) {
#pragma unroll
                            for (int k = 0; k < 8; k++) o[k >> 2][k & 3] = __byte_perm(v[k >> 2][ws + (k & 3)], v[k >> 2][ws + (k & 3) + 1], (cls & 1) ? 0x5432 : 0x3210);
                        };
                        auto mir = [&](int ws) {
#pragma unroll
                            for (int k = 8; k < 16; k++) o[k >> 2][k & 3] = __byte_perm(v[k >> 2][ws + 3 - (k & 3)], v[k >> 2][ws + 4 - (k & 3)], (cls & 1) ? 0x1032 : 0x3254);
                        };
                        switch ((cls >> 1) & 3) { case 0: fwd(0); break; case 1: fwd(1); break; case 2: fwd(2); break; default: fwd(3); }
                        switch (((1 - cls) >> 1) & 3) { case 0: mir(0); break; case 1: mir(1); break; case 2: mir(2); break; default: mir(3); }
                        if (lane == 0) {
                            o[0][0] = pack2(fmaf(pl ? -0.5f : 0.5f, bf_lo(e0), 0.5f * bf_lo(o[0][0])), bf_hi(o[0][0]));
                            o[2][0] = pack2(fmaf(pl ? -0.5f : 0.5f, bf_lo(e1), 0.5f * bf_lo(o[2][0])), bf_hi(o[2][0]));
                        }
                        __syncwarp();
#pragma unroll
                        for (int i = 0; i < 4; i++)
                            sts128u((i < 2 ? dp : mp) + (i & 1) * 512 + ((lane * 16) ^ ((lane << 1) & 48)), o[i][0], o[i][1], o[i][2], o[i][3]);
                    }
                    if (ps) fence_proxy_async_smem();
                    mbar_arrive(bars + 8 * (BAR_C + ps));
                    if (tid == 320) PROF(ps ? 12 : 28);
                }
                if (!elect()) return;
                if (w == 2) {
                    {
#pragma unroll 1
                        for (int i = 0; i < 8; i++) {
                            if (!(i & 3)) { mbar_wait(bars + 8 * BAR_VW, i >> 2); if (!i && !HF) fence_proxy_async_smem(); }
                            else pause(PACE_V);
                            if (!(real_cls && (i & 1))) tma_store_4d(&mapU2, sb + OFF_U + (i & 1) * 16384 + (i >> 1) * 4096, 0, 0, (i >> 1) * 4, b == 128 ? 1 : 2 * b + (i & 1));
                        }
                        bulk_commit();
                        bulk_wait_read();
                        mbar_arrive(bars + 8 * BAR_U);
                        bulk_wait0();
                        signal_counter(&g_cnt[CNT_V * CS]);
                        PROF(13);
                        if (main_cta) {
                            wait_counter(&g_cnt[CNT_V * CS + (b & (NREP - 1)) * RS], epoch * 129);
                            mbar_arrive(bars + 8 * (BAR_F + 2));
                            PROF(14);
                        }
                    }
                }
            }
        }
    }
}

typedef CUresult (*PFN_encodeTiled)(CUtensorMap*, CUtensorMapDataType, cuuint32_t, void*, const cuuint64_t*, const cuuint64_t*,
                                    const cuuint32_t*, const cuuint32_t*, CUtensorMapInterleave, CUtensorMapSwizzle,
                                    CUtensorMapL2promotion, CUtensorMapFloatOOBfill);

static CUtensorMap make_map(PFN_encodeTiled enc, const void* ptr, int rank, const cuuint64_t* dims, const cuuint64_t* strides, const cuuint32_t* box,
                            CUtensorMapSwizzle sw = CU_TENSOR_MAP_SWIZZLE_128B, CUtensorMapDataType dt = CU_TENSOR_MAP_DATA_TYPE_BFLOAT16) {
    CUtensorMap m;
    cuuint32_t es[5] = {1, 1, 1, 1, 1};
    enc(&m, dt, rank, (void*)ptr, dims, strides, box, es, CU_TENSOR_MAP_INTERLEAVE_NONE,
        sw, CU_TENSOR_MAP_L2_PROMOTION_L2_128B, CU_TENSOR_MAP_FLOAT_OOB_FILL_NONE);
    return m;
}

extern "C" void kernel_launch(void* const* d_in, const int* in_sizes, int n_in, void* d_out, int out_size) {
    const bf16* x = (const bf16*)d_in[0];
    const bf16* wr = (const bf16*)d_in[1];
    const bf16* wi = (const bf16*)d_in[2];
    const bf16* Bre = (const bf16*)d_in[6];
    const bf16* Bim = (const bf16*)d_in[7];
    const bf16* Cre = (const bf16*)d_in[8];
    const bf16* Cim = (const bf16*)d_in[9];

    void* fn = nullptr;
    cudaDriverEntryPointQueryResult st;
    cudaGetDriverEntryPoint("cuTensorMapEncodeTiled", &fn, cudaEnableDefault, &st);
    PFN_encodeTiled enc = (PFN_encodeTiled)fn;
    void *p_hT, *p_U;
    cudaGetSymbolAddress(&p_hT, g_hT);
    cudaGetSymbolAddress(&p_U, g_U);

    Params P;
    P.lam_re = (const bf16*)d_in[4]; P.lam_im = (const bf16*)d_in[5]; P.log_dt = (const bf16*)d_in[10];
    P.dskip = (const bf16*)d_in[11]; P.gate_w = (const bf16*)d_in[12]; P.c_re = Cre; P.c_im = Cim; P.b_re = Bre; P.b_im = Bim; P.x = x;
    P.swapB = Bim < Bre;

    CUtensorMap mB, mX, mCre, mCim, mXs, mU0, mV, mU2, mXe, mO, mWr, mWi, mH;
    {
        cuuint64_t d[4] = {64, 2052, 2, 4}, s[3] = {128, 262656, 525312};
        cuuint32_t bx[4] = {64, 9, 1, 4};
        mWr = make_map(enc, wr, 4, d, s, bx, CU_TENSOR_MAP_SWIZZLE_NONE);
        mWi = make_map(enc, wi, 4, d, s, bx, CU_TENSOR_MAP_SWIZZLE_NONE);
    }
    {
        cuuint64_t d[3] = {128, 32, 256}, s[2] = {1024, 32768};
        cuuint32_t bx[3] = {128, 1, 16 / HN};
        mH = make_map(enc, p_hT, 3, d, s, bx, CU_TENSOR_MAP_SWIZZLE_NONE, CU_TENSOR_MAP_DATA_TYPE_UINT64);
    }
    {
        const bf16* lo = P.swapB ? Bim : Bre; const bf16* hi = P.swapB ? Bre : Bim;
        cuuint64_t d[4] = {1024, 8, 2, 128}, s[3] = {2048, (cuuint64_t)((const char*)hi - (const char*)lo), 16384};
        cuuint32_t bx[4] = {64, 8, 2, 8};
        mB = make_map(enc, lo, 4, d, s, bx);
    }
    {
        cuuint64_t d[4] = {1024, 2, 4, 976}, s[3] = {2048, 32 * 2048, 2 * 2048};
        cuuint32_t bx[4] = {64, 2, 4, 16};
        mX = make_map(enc, x, 4, d, s, bx);
    }
    {
        cuuint64_t d[3] = {64, 1024, 16}, s[2] = {2048, 128};
        cuuint32_t bx[3] = {64, 128, 1};
        mCre = make_map(enc, Cre, 3, d, s, bx);
        mCim = make_map(enc, Cim, 3, d, s, bx);
    }
    {
        cuuint64_t d[3] = {64, 256, 128}, s[2] = {16384, 128};
        cuuint32_t bx[3] = {64, 64, 2};
        mV = make_map(enc, p_U, 3, d, s, bx);
    }
    {
        cuuint64_t d[5] = {1024, 8, 2, 16, 8}, s[4] = {16 * 2048, 8 * 2048, 128 * 2048, 2048};
        cuuint32_t bx[5] = {64, 8, 2, 4, 1};
        mXe = make_map(enc, x, 5, d, s, bx);
    }
    {
        cuuint64_t d[3] = {1024, 256, 8}, s[2] = {8 * 4096, 4096};
        cuuint32_t bx[3] = {32, 16, 1};
        mO = make_map(enc, d_out, 3, d, s, bx, CU_TENSOR_MAP_SWIZZLE_128B, CU_TENSOR_MAP_DATA_TYPE_FLOAT32);
    }
    {
        cuuint64_t d[4] = {1024, 64, 4, 8}, s[3] = {32 * 2048, 8 * 2048, 2048};
        cuuint32_t bx[4] = {64, 64, 1, 1};
        mXs = make_map(enc, x, 4, d, s, bx);
    }
    {
        cuuint64_t d[4] = {1024, 128, 2, 8}, s[3] = {32768, 16384, 2048};
        cuuint32_t bx[4] = {64, UN == 4 ? 16 : 32, UN == 1 ? 2 : 1, 1};
        mU0 = make_map(enc, p_U, 4, d, s, bx);
    }
    {
        cuuint64_t d[4] = {64, 8, 16, 256}, s[3] = {2048, 128, 16384};
        cuuint32_t bx[4] = {64, 8, 4, 1};
        mU2 = make_map(enc, p_U, 4, d, s, bx);
    }
    cudaFuncSetAttribute(fused_kernel, cudaFuncAttributeMaxDynamicSharedMemorySize, SMEM_BYTES);
    fused_kernel<<<130, 384, SMEM_BYTES, cudaStreamPerThread>>>(mB, mX, mXs, mU0, mU2, mXe, mCre, mCim, mV, mO, mWr, mWi, mH, P);
}
```

```cpp
#include <cuda_runtime.h>
#include <cuda_bf16.h>
#include <cuda.h>
#include <stdint.h>

typedef __nv_bfloat16 bf16;

__device__ const __align__(128) uint32_t c_tab[10240] = {
0x3f803f80,0xbf803f80,0x3f803f80,0xbf803f80,0x3f803f80,0xbf803f80,0x3f803f80,0xbf803f80,0x3f803f80,0xbf803f80,0x3f803f80,0xbf803f80,
0x3f803f80,0xbf803f80,0x3f803f80,0xbf803f80,0x3f7f3f80,0xbdc98000,0x3f223f35,0xbf46bf35,0x3f753f7b,0xbe95be48,0x3ef13f0e,0xbf62bf55,
0x3f623f6d,0xbef1bec4,0x3e953ec4,0xbf75bf6d,0x3f463f55,0xbf22bf0e,0x3dc93e48,0xbf7fbf7b,0x3f7b3f80,0xbe488000,0xbe480000,0xbf7bbf80,
0x3f553f6d,0xbf0ebec4,0xbf0ebec4,0xbf55bf6d,0x3f0e3f35,0xbf55bf35,0xbf55bf35,0xbf0ebf35,0x3e483ec4,0xbf7bbf6d,0xbf7bbf6d,0xbe48bec4,
0x3f753f80,0xbe958000,0xbf62bf35,0xbef1bf35,0x3f223f55,0xbf46bf0e,0xbf7fbf7b,0x3dc9be48,0x3dc93ec4,0xbf7fbf6d,0xbf46bf6d,0x3f223ec4,
0xbef1be48,0xbf62bf7b,0xbe95bf0e,0x3f753f55,0x3f6d3f80,0xbec48000,0xbf6dbf80,0x3ec48000,0x3ec43f35,0xbf6dbf35,0xbec4bf35,0x3f6d3f35,
0xbec40000,0xbf6dbf80,0x3ec40000,0x3f6d3f80,0xbf6dbf35,0xbec4bf35,0x3f6d3f35,0x3ec43f35,0x3f623f80,0xbef18000,0xbe95bf35,0x3f753f35,
0x3dc93f0e,0xbf7fbf55,0x3f223e48,0x3f463f7b,0xbf46bec4,0xbf22bf6d,0x3f7f3f6d,0xbdc93ec4,0xbf75bf7b,0x3e95be48,0x3ef13f55,0xbf62bf0e,
0x3f553f80,0xbf0e8000,0x3f0e0000,0x3f553f80,0xbe483ec4,0xbf7bbf6d,0x3f7b3f6d,0xbe483ec4,0xbf7bbf35,0xbe48bf35,0x3e483f35,0xbf7bbf35,
0xbf0ebf6d,0x3f553ec4,0xbf55bec4,0xbf0ebf6d,0x3f463f80,0xbf228000,0x3f7f3f35,0x3dc93f35,0xbef13e48,0xbf62bf7b,0x3e953f55,0xbf75bf0e,
0xbf75bf6d,0x3e95bec4,0xbf62bec4,0xbef1bf6d,0x3dc9bf0e,0x3f7f3f55,0xbf22bf7b,0x3f463e48,0x3f353f80,0xbf358000,0x3f353f80,0xbf358000,
0xbf350000,0xbf35bf80,0xbf350000,0xbf35bf80,0xbf35bf80,0x3f358000,0xbf35bf80,0x3f358000,0x3f350000,0x3f353f80,0x3f350000,0x3f353f80,
0x3f223f80,0xbf468000,0xbdc93f35,0xbf7fbf35,0xbf62be48,0xbef1bf7b,0xbf75bf55,0x3e95bf0e,0xbe95bf6d,0x3f753ec4,0x3ef1bec4,0x3f623f6d,
0x3f7f3f0e,0x3dc93f55,0x3f463f7b,0xbf223e48,0x3f0e3f80,0xbf558000,0xbf550000,0xbf0ebf80,0xbf7bbec4,0xbe48bf6d,0xbe48bf6d,0x3f7b3ec4,
0x3e48bf35,0x3f7b3f35,0x3f7b3f35,0xbe483f35,0x3f553f6d,0xbf0e3ec4,0xbf0e3ec4,0xbf55bf6d,0x3ef13f80,0xbf628000,0xbf75bf35,0x3e95bf35,
0xbf7fbf0e,0x3dc9bf55,0x3f46be48,0x3f223f7b,0x3f22bec4,0x3f463f6d,0x3dc93f6d,0xbf7fbec4,0x3e953f7b,0xbf75be48,0xbf62bf55,0x3ef1bf0e,
0x3ec43f80,0xbf6d8000,0xbec4bf80,0x3f6d8000,0xbf6dbf35,0x3ec4bf35,0x3f6d3f35,0xbec43f35,0x3f6d0000,0x3ec43f80,0xbf6d0000,0xbec4bf80,
0xbec43f35,0xbf6dbf35,0x3ec4bf35,0x3f6d3f35,0x3e953f80,0xbf758000,0x3ef1bf35,0x3f623f35,0xbf46bf55,0x3f22bf0e,0x3dc93f7b,0xbf7fbe48,
0x3f7f3ec4,0xbdc93f6d,0xbf22bf6d,0x3f46bec4,0xbf623e48,0xbef1bf7b,0x3f753f0e,0xbe953f55,0x3e483f80,0xbf7b8000,0x3f7b0000,0x3e483f80,
0xbf0ebf6d,0x3f55bec4,0xbf553ec4,0xbf0ebf6d,0x3f553f35,0xbf0e3f35,0x3f0ebf35,0x3f553f35,0xbf7bbec4,0x3e48bf6d,0xbe483f6d,0xbf7bbec4,
0x3dc93f80,0xbf7f8000,0x3f463f35,0xbf223f35,0xbe95bf7b,0x3f75be48,0xbf62bf0e,0x3ef1bf55,0x3ef13f6d,0xbf623ec4,0x3f753ec4,0xbe953f6d,
0xbf22bf55,0x3f46bf0e,0xbf7fbe48,0x3dc9bf7b,0x3f80,0xbf808000,0x3f80,0xbf808000,0xbf80,0x3f808000,0xbf80,0x3f808000,
0x3f80,0xbf808000,0x3f80,0xbf808000,0xbf80,0x3f808000,0xbf80,0x3f808000,0xbdc93f80,0xbf7f8000,0xbf463f35,0xbf22bf35,
0x3e95bf7b,0x3f753e48,0x3f62bf0e,0x3ef13f55,0xbef13f6d,0xbf62bec4,0xbf753ec4,0xbe95bf6d,0x3f22bf55,0x3f463f0e,0x3f7fbe48,0x3dc93f7b,
0xbe483f80,0xbf7b8000,0xbf7b0000,0x3e48bf80,0x3f0ebf6d,0x3f553ec4,0x3f553ec4,0xbf0e3f6d,0xbf553f35,0xbf0ebf35,0xbf0ebf35,0x3f55bf35,
0x3f7bbec4,0x3e483f6d,0x3e483f6d,0xbf7b3ec4,0xbe953f80,0xbf758000,0xbef1bf35,0x3f62bf35,0x3f46bf55,0x3f223f0e,0xbdc93f7b,0xbf7f3e48,
0xbf7f3ec4,0xbdc9bf6d,0x3f22bf6d,0x3f463ec4,0x3f623e48,0xbef13f7b,0xbf753f0e,0xbe95bf55,0xbec43f80,0xbf6d8000,0x3ec4bf80,0x3f6d8000,
0x3f6dbf35,0x3ec43f35,0xbf6d3f35,0xbec4bf35,0xbf6d0000,0x3ec4bf80,0x3f6d0000,0xbec43f80,0x3ec43f35,0xbf6d3f35,0xbec4bf35,0x3f6dbf35,
0xbef13f80,0xbf628000,0x3f75bf35,0x3e953f35,0x3f7fbf0e,0x3dc93f55,0xbf46be48,0x3f22bf7b,0xbf22bec4,0x3f46bf6d,0xbdc93f6d,0xbf7f3ec4,
0xbe953f7b,0xbf753e48,0x3f62bf55,0x3ef13f0e,0xbf0e3f80,0xbf558000,0x3f550000,0xbf0e3f80,0x3f7bbec4,0xbe483f6d,0x3e48bf6d,0x3f7bbec4,
0xbe48bf35,0x3f7bbf35,0xbf7b3f35,0xbe48bf35,0xbf553f6d,0xbf0ebec4,0x3f0e3ec4,0xbf553f6d,0xbf223f80,0xbf468000,0x3dc93f35,0xbf7f3f35,
0x3f62be48,0xbef13f7b,0x3f75bf55,0x3e953f0e,0x3e95bf6d,0x3f75bec4,0xbef1bec4,0x3f62bf6d,0xbf7f3f0e,0x3dc9bf55,0xbf463f7b,0xbf22be48,
0xbf353f80,0xbf358000,0xbf353f80,0xbf358000,0x3f350000,0xbf353f80,0x3f350000,0xbf353f80,0x3f35bf80,0x3f358000,0x3f35bf80,0x3f358000,
0xbf350000,0x3f35bf80,0xbf350000,0x3f35bf80,0xbf463f80,0xbf228000,0xbf7f3f35,0x3dc9bf35,0x3ef13e48,0xbf623f7b,0xbe953f55,0xbf753f0e,
0x3f75bf6d,0x3e953ec4,0x3f62bec4,0xbef13f6d,0xbdc9bf0e,0x3f7fbf55,0x3f22bf7b,0x3f46be48,0xbf553f80,0xbf0e8000,0xbf0e0000,0x3f55bf80,
0x3e483ec4,0xbf7b3f6d,0xbf7b3f6d,0xbe48bec4,0x3f7bbf35,0xbe483f35,0xbe483f35,0xbf7b3f35,0x3f0ebf6d,0x3f55bec4,0x3f55bec4,0xbf0e3f6d,
0xbf623f80,0xbef18000,0x3e95bf35,0x3f75bf35,0xbdc93f0e,0xbf7f3f55,0xbf223e48,0x3f46bf7b,0x3f46bec4,0xbf223f6d,0xbf7f3f6d,0xbdc9bec4,
0x3f75bf7b,0x3e953e48,0xbef13f55,0xbf623f0e,0xbf6d3f80,0xbec48000,0x3f6dbf80,0x3ec48000,0xbec43f35,0xbf6d3f35,0x3ec4bf35,0x3f6dbf35,
0x3ec40000,0xbf6d3f80,0xbec40000,0x3f6dbf80,0x3f6dbf35,0xbec43f35,0xbf6d3f35,0x3ec4bf35,0xbf753f80,0xbe958000,0x3f62bf35,0xbef13f35,
0xbf223f55,0xbf463f0e,0x3f7fbf7b,0x3dc93e48,0xbdc93ec4,0xbf7f3f6d,0x3f46bf6d,0x3f22bec4,0x3ef1be48,0xbf623f7b,0x3e95bf0e,0x3f75bf55,
0xbf7b3f80,0xbe488000,0x3e480000,0xbf7b3f80,0xbf553f6d,0xbf0e3ec4,0x3f0ebec4,0xbf553f6d,0xbf0e3f35,0xbf553f35,0x3f55bf35,0xbf0e3f35,
0xbe483ec4,0xbf7b3f6d,0x3f7bbf6d,0xbe483ec4,0xbf7f3f80,0xbdc98000,0xbf223f35,0xbf463f35,0xbf753f7b,0xbe953e48,0xbef13f0e,0xbf623f55,
0xbf623f6d,0xbef13ec4,0xbe953ec4,0xbf753f6d,0xbf463f55,0xbf223f0e,0xbdc93e48,0xbf7f3f7b,0x3f803f80,0xbf803f80,0x3f803f80,0xbf803f80,
0x3f803f80,0xbf803f80,0x3f803f80,0xbf803f80,0x3f803f80,0xbf803f80,0x3f803f80,0xbf803f80,0x3f803f80,0xbf803f80,0x3f803f80,0xbf803f80,
0xbdc90000,0xbf7fbf80,0xbf46bf35,0xbf22bf35,0xbe95be48,0xbf75bf7b,0xbf62bf55,0xbef1bf0e,0xbef1bec4,0xbf62bf6d,0xbf75bf6d,0xbe95bec4,
0xbf22bf0e,0xbf46bf55,0xbf7fbf7b,0xbdc9be48,0xbf7bbf80,0x3e488000,0x3e480000,0x3f7b3f80,0xbf55bf6d,0x3f0e3ec4,0x3f0e3ec4,0x3f553f6d,
0xbf0ebf35,0x3f553f35,0x3f553f35,0x3f0e3f35,0xbe48bec4,0x3f7b3f6d,0x3f7b3f6d,0x3e483ec4,0x3e950000,0x3f753f80,0x3ef13f35,0xbf62bf35,
0x3f463f0e,0x3f223f55,0xbdc93e48,0xbf7fbf7b,0x3f7f3f6d,0x3dc93ec4,0xbf22bec4,0xbf46bf6d,0x3f623f7b,0xbef1be48,0xbf75bf55,0xbe95bf0e,
0x3f6d3f80,0xbec48000,0xbf6dbf80,0x3ec48000,0x3ec43f35,0xbf6dbf35,0xbec4bf35,0x3f6d3f35,0xbec40000,0xbf6dbf80,0x3ec40000,0x3f6d3f80,
0xbf6dbf35,0xbec4bf35,0x3f6d3f35,0x3ec43f35,0xbef10000,0xbf62bf80,0x3f753f35,0x3e953f35,0xbf7fbf55,0xbdc9bf0e,0x3f463f7b,0xbf22be48,
0xbf22bf6d,0x3f463ec4,0xbdc93ec4,0xbf7fbf6d,0x3e95be48,0x3f753f7b,0xbf62bf0e,0xbef1bf55,0xbf55bf80,0x3f0e8000,0xbf0e0000,0xbf55bf80,
0x3e48bec4,0x3f7b3f6d,0xbf7bbf6d,0x3e48bec4,0x3f7b3f35,0x3e483f35,0xbe48bf35,0x3f7b3f35,0x3f0e3f6d,0xbf55bec4,0x3f553ec4,0x3f0e3f6d,
0x3f220000,0x3f463f80,0xbdc9bf35,0x3f7f3f35,0x3f623f7b,0xbef13e48,0x3f753f0e,0x3e953f55,0xbe953ec4,0xbf75bf6d,0x3ef13f6d,0xbf62bec4,
0xbf7fbf55,0x3dc9bf0e,0xbf46be48,0xbf22bf7b,0x3f353f80,0xbf358000,0x3f353f80,0xbf358000,0xbf350000,0xbf35bf80,0xbf350000,0xbf35bf80,
0xbf35bf80,0x3f358000,0xbf35bf80,0x3f358000,0x3f350000,0x3f353f80,0x3f350000,0x3f353f80,0xbf460000,0xbf22bf80,0xbf7fbf35,0x3dc9bf35,
0xbef1bf7b,0x3f623e48,0x3e95bf0e,0x3f753f55,0x3f753ec4,0x3e953f6d,0x3f623f6d,0xbef13ec4,0x3dc93f55,0xbf7fbf0e,0xbf223e48,0xbf46bf7b,
0xbf0ebf80,0x3f558000,0x3f550000,0x3f0e3f80,0x3f7b3ec4,0x3e483f6d,0x3e483f6d,0xbf7bbec4,0xbe483f35,0xbf7bbf35,0xbf7bbf35,0x3e48bf35,
0xbf55bf6d,0x3f0ebec4,0x3f0ebec4,0x3f553f6d,0x3f620000,0x3ef13f80,0xbe953f35,0xbf75bf35,0xbdc93f55,0xbf7fbf0e,0xbf22bf7b,0x3f46be48,
0xbf46bf6d,0x3f22bec4,0x3f7f3ec4,0x3dc93f6d,0x3f753e48,0x3e953f7b,0xbef13f0e,0xbf62bf55,0x3ec43f80,0xbf6d8000,0xbec4bf80,0x3f6d8000,
0xbf6dbf35,0x3ec4bf35,0x3f6d3f35,0xbec43f35,0x3f6d0000,0x3ec43f80,0xbf6d0000,0xbec4bf80,0xbec43f35,0xbf6dbf35,0x3ec4bf35,0x3f6d3f35,
0xbf750000,0xbe95bf80,0x3f623f35,0xbef13f35,0x3f22bf0e,0x3f463f55,0xbf7fbe48,0xbdc9bf7b,0xbdc93f6d,0xbf7fbec4,0x3f46bec4,0x3f223f6d,
0xbef1bf7b,0x3f62be48,0xbe953f55,0xbf75bf0e,0xbe48bf80,0x3f7b8000,0xbf7b0000,0xbe48bf80,0x3f0e3f6d,0xbf553ec4,0x3f55bec4,0x3f0e3f6d,
0xbf55bf35,0x3f0ebf35,0xbf0e3f35,0xbf55bf35,0x3f7b3ec4,0xbe483f6d,0x3e48bf6d,0x3f7b3ec4,0x3f7f0000,0x3dc93f80,0x3f22bf35,0x3f463f35,
0xbf753e48,0xbe95bf7b,0xbef13f55,0xbf62bf0e,0x3f62bec4,0x3ef13f6d,0x3e95bf6d,0x3f753ec4,0xbf463f0e,0xbf22bf55,0xbdc93f7b,0xbf7fbe48,
0x3f80,0xbf808000,0x3f80,0xbf808000,0xbf80,0x3f808000,0xbf80,0x3f808000,0x3f80,0xbf808000,0x3f80,0xbf808000,
0xbf80,0x3f808000,0xbf80,0x3f808000,0xbf7f0000,0x3dc9bf80,0xbf22bf35,0x3f46bf35,0x3f753e48,0xbe953f7b,0x3ef13f55,0xbf623f0e,
0xbf62bec4,0x3ef1bf6d,0xbe95bf6d,0x3f75bec4,0x3f463f0e,0xbf223f55,0x3dc93f7b,0xbf7f3e48,0x3e48bf80,0x3f7b8000,0x3f7b0000,0xbe483f80,
0xbf0e3f6d,0xbf55bec4,0xbf55bec4,0x3f0ebf6d,0x3f55bf35,0x3f0e3f35,0x3f0e3f35,0xbf553f35,0xbf7b3ec4,0xbe48bf6d,0xbe48bf6d,0x3f7bbec4,
0x3f750000,0xbe953f80,0xbf623f35,0xbef1bf35,0xbf22bf0e,0x3f46bf55,0x3f7fbe48,0xbdc93f7b,0x3dc93f6d,0xbf7f3ec4,0xbf46bec4,0x3f22bf6d,
0x3ef1bf7b,0x3f623e48,0x3e953f55,0xbf753f0e,0xbec43f80,0xbf6d8000,0x3ec4bf80,0x3f6d8000,0x3f6dbf35,0x3ec43f35,0xbf6d3f35,0xbec4bf35,
0xbf6d0000,0x3ec4bf80,0x3f6d0000,0xbec43f80,0x3ec43f35,0xbf6d3f35,0xbec4bf35,0x3f6dbf35,0xbf620000,0x3ef1bf80,0x3e953f35,0xbf753f35,
0x3dc93f55,0xbf7f3f0e,0x3f22bf7b,0x3f463e48,0x3f46bf6d,0x3f223ec4,0xbf7f3ec4,0x3dc9bf6d,0xbf753e48,0x3e95bf7b,0x3ef13f0e,0xbf623f55,
0x3f0ebf80,0x3f558000,0xbf550000,0x3f0ebf80,0xbf7b3ec4,0x3e48bf6d,0xbe483f6d,0xbf7b3ec4,0x3e483f35,0xbf7b3f35,0x3f7bbf35,0x3e483f35,
0x3f55bf6d,0x3f0e3ec4,0xbf0ebec4,0x3f55bf6d,0x3f460000,0xbf223f80,0x3f7fbf35,0x3dc93f35,0x3ef1bf7b,0x3f62be48,0xbe95bf0e,0x3f75bf55,
0xbf753ec4,0x3e95bf6d,0xbf623f6d,0xbef1bec4,0xbdc93f55,0xbf7f3f0e,0x3f223e48,0xbf463f7b,0xbf353f80,0xbf358000,0xbf353f80,0xbf358000,
0x3f350000,0xbf353f80,0x3f350000,0xbf353f80,0x3f35bf80,0x3f358000,0x3f35bf80,0x3f358000,0xbf350000,0x3f35bf80,0xbf350000,0x3f35bf80,
0xbf220000,0x3f46bf80,0x3dc9bf35,0x3f7fbf35,0xbf623f7b,0xbef1be48,0xbf753f0e,0x3e95bf55,0x3e953ec4,0xbf753f6d,0xbef13f6d,0xbf623ec4,
0x3f7fbf55,0x3dc93f0e,0x3f46be48,0xbf223f7b,0x3f55bf80,0x3f0e8000,0x3f0e0000,0xbf553f80,0xbe48bec4,0x3f7bbf6d,0x3f7bbf6d,0x3e483ec4,
0xbf7b3f35,0x3e48bf35,0x3e48bf35,0x3f7bbf35,0xbf0e3f6d,0xbf553ec4,0xbf553ec4,0x3f0ebf6d,0x3ef10000,0xbf623f80,0xbf753f35,0x3e95bf35,
0x3f7fbf55,0xbdc93f0e,0xbf463f7b,0xbf223e48,0x3f22bf6d,0x3f46bec4,0x3dc93ec4,0xbf7f3f6d,0xbe95be48,0x3f75bf7b,0x3f62bf0e,0xbef13f55,
0xbf6d3f80,0xbec48000,0x3f6dbf80,0x3ec48000,0xbec43f35,0xbf6d3f35,0x3ec4bf35,0x3f6dbf35,0x3ec40000,0xbf6d3f80,0xbec40000,0x3f6dbf80,
0x3f6dbf35,0xbec43f35,0xbf6d3f35,0x3ec4bf35,0xbe950000,0x3f75bf80,0xbef13f35,0xbf623f35,0xbf463f0e,0x3f22bf55,0x3dc93e48,0xbf7f3f7b,
0xbf7f3f6d,0x3dc9bec4,0x3f22bec4,0xbf463f6d,0xbf623f7b,0xbef13e48,0x3f75bf55,0xbe953f0e,0x3f7bbf80,0x3e488000,0xbe480000,0x3f7bbf80,
0x3f55bf6d,0x3f0ebec4,0xbf0e3ec4,0x3f55bf6d,0x3f0ebf35,0x3f55bf35,0xbf553f35,0x3f0ebf35,0x3e48bec4,0x3f7bbf6d,0xbf7b3f6d,0x3e48bec4,
0x3dc90000,0xbf7f3f80,0x3f46bf35,0xbf223f35,0x3e95be48,0xbf753f7b,0x3f62bf55,0xbef13f0e,0x3ef1bec4,0xbf623f6d,0x3f75bf6d,0xbe953ec4,
0x3f22bf0e,0xbf463f55,0x3f7fbf7b,0xbdc93e48,0x3f803f80,0xbf803f80,0x3f803f80,0xbf803f80,0x3f803f80,0xbf803f80,0x3f803f80,0xbf803f80,
0x3f803f80,0xbf803f80,0x3f803f80,0xbf803f80,0x3f803f80,0xbf803f80,0x3f803f80,0xbf803f80,0xbf7fbf80,0x3dc98000,0xbf22bf35,0x3f463f35,
0xbf75bf7b,0x3e953e48,0xbef1bf0e,0x3f623f55,0xbf62bf6d,0x3ef13ec4,0xbe95bec4,0x3f753f6d,0xbf46bf55,0x3f223f0e,0xbdc9be48,0x3f7f3f7b,
0x3f7b3f80,0xbe488000,0xbe480000,0xbf7bbf80,0x3f553f6d,0xbf0ebec4,0xbf0ebec4,0xbf55bf6d,0x3f0e3f35,0xbf55bf35,0xbf55bf35,0xbf0ebf35,
0x3e483ec4,0xbf7bbf6d,0xbf7bbf6d,0xbe48bec4,0xbf75bf80,0x3e958000,0x3f623f35,0x3ef13f35,0xbf22bf55,0x3f463f0e,0x3f7f3f7b,0xbdc93e48,
0xbdc9bec4,0x3f7f3f6d,0x3f463f6d,0xbf22bec4,0x3ef13e48,0x3f623f7b,0x3e953f0e,0xbf75bf55,0x3f6d3f80,0xbec48000,0xbf6dbf80,0x3ec48000,
0x3ec43f35,0xbf6dbf35,0xbec4bf35,0x3f6d3f35,0xbec40000,0xbf6dbf80,0x3ec40000,0x3f6d3f80,0xbf6dbf35,0xbec4bf35,0x3f6d3f35,0x3ec43f35,
0xbf62bf80,0x3ef18000,0x3e953f35,0xbf75bf35,0xbdc9bf0e,0x3f7f3f55,0xbf22be48,0xbf46bf7b,0x3f463ec4,0x3f223f6d,0xbf7fbf6d,0x3dc9bec4,
0x3f753f7b,0xbe953e48,0xbef1bf55,0x3f623f0e,0x3f553f80,0xbf0e8000,0x3f0e0000,0x3f553f80,0xbe483ec4,0xbf7bbf6d,0x3f7b3f6d,0xbe483ec4,
0xbf7bbf35,0xbe48bf35,0x3e483f35,0xbf7bbf35,0xbf0ebf6d,0x3f553ec4,0xbf55bec4,0xbf0ebf6d,0xbf46bf80,0x3f228000,0xbf7fbf35,0xbdc9bf35,
0x3ef1be48,0x3f623f7b,0xbe95bf55,0x3f753f0e,0x3f753f6d,0xbe953ec4,0x3f623ec4,0x3ef13f6d,0xbdc93f0e,0xbf7fbf55,0x3f223f7b,0xbf46be48,
0x3f353f80,0xbf358000,0x3f353f80,0xbf358000,0xbf350000,0xbf35bf80,0xbf350000,0xbf35bf80,0xbf35bf80,0x3f358000,0xbf35bf80,0x3f358000,
0x3f350000,0x3f353f80,0x3f350000,0x3f353f80,0xbf22bf80,0x3f468000,0x3dc9bf35,0x3f7f3f35,0x3f623e48,0x3ef13f7b,0x3f753f55,0xbe953f0e,
0x3e953f6d,0xbf75bec4,0xbef13ec4,0xbf62bf6d,0xbf7fbf0e,0xbdc9bf55,0xbf46bf7b,0x3f22be48,0x3f0e3f80,0xbf558000,0xbf550000,0xbf0ebf80,
0xbf7bbec4,0xbe48bf6d,0xbe48bf6d,0x3f7b3ec4,0x3e48bf35,0x3f7b3f35,0x3f7b3f35,0xbe483f35,0x3f553f6d,0xbf0e3ec4,0xbf0e3ec4,0xbf55bf6d,
0xbef1bf80,0x3f628000,0x3f753f35,0xbe953f35,0x3f7f3f0e,0xbdc93f55,0xbf463e48,0xbf22bf7b,0xbf223ec4,0xbf46bf6d,0xbdc9bf6d,0x3f7f3ec4,
0xbe95bf7b,0x3f753e48,0x3f623f55,0xbef13f0e,0x3ec43f80,0xbf6d8000,0xbec4bf80,0x3f6d8000,0xbf6dbf35,0x3ec4bf35,0x3f6d3f35,0xbec43f35,
0x3f6d0000,0x3ec43f80,0xbf6d0000,0xbec4bf80,0xbec43f35,0xbf6dbf35,0x3ec4bf35,0x3f6d3f35,0xbe95bf80,0x3f758000,0xbef13f35,0xbf62bf35,
0x3f463f55,0xbf223f0e,0xbdc9bf7b,0x3f7f3e48,0xbf7fbec4,0x3dc9bf6d,0x3f223f6d,0xbf463ec4,0x3f62be48,0x3ef13f7b,0xbf75bf0e,0x3e95bf55,
0x3e483f80,0xbf7b8000,0x3f7b0000,0x3e483f80,0xbf0ebf6d,0x3f55bec4,0xbf553ec4,0xbf0ebf6d,0x3f553f35,0xbf0e3f35,0x3f0ebf35,0x3f553f35,
0xbf7bbec4,0x3e48bf6d,0xbe483f6d,0xbf7bbec4,0xbdc9bf80,0x3f7f8000,0xbf46bf35,0x3f22bf35,0x3e953f7b,0xbf753e48,0x3f623f0e,0xbef13f55,
0xbef1bf6d,0x3f62bec4,0xbf75bec4,0x3e95bf6d,0x3f223f55,0xbf463f0e,0x3f7f3e48,0xbdc93f7b,0x3f80,0xbf808000,0x3f80,0xbf808000,
0xbf80,0x3f808000,0xbf80,0x3f808000,0x3f80,0xbf808000,0x3f80,0xbf808000,0xbf80,0x3f808000,0xbf80,0x3f808000,
0x3dc9bf80,0x3f7f8000,0x3f46bf35,0x3f223f35,0xbe953f7b,0xbf75be48,0xbf623f0e,0xbef1bf55,0x3ef1bf6d,0x3f623ec4,0x3f75bec4,0x3e953f6d,
0xbf223f55,0xbf46bf0e,0xbf7f3e48,0xbdc9bf7b,0xbe483f80,0xbf7b8000,0xbf7b0000,0x3e48bf80,0x3f0ebf6d,0x3f553ec4,0x3f553ec4,0xbf0e3f6d,
0xbf553f35,0xbf0ebf35,0xbf0ebf35,0x3f55bf35,0x3f7bbec4,0x3e483f6d,0x3e483f6d,0xbf7b3ec4,0x3e95bf80,0x3f758000,0x3ef13f35,0xbf623f35,
0xbf463f55,0xbf22bf0e,0x3dc9bf7b,0x3f7fbe48,0x3f7fbec4,0x3dc93f6d,0xbf223f6d,0xbf46bec4,0xbf62be48,0x3ef1bf7b,0x3f75bf0e,0x3e953f55,
0xbec43f80,0xbf6d8000,0x3ec4bf80,0x3f6d8000,0x3f6dbf35,0x3ec43f35,0xbf6d3f35,0xbec4bf35,0xbf6d0000,0x3ec4bf80,0x3f6d0000,0xbec43f80,
0x3ec43f35,0xbf6d3f35,0xbec4bf35,0x3f6dbf35,0x3ef1bf80,0x3f628000,0xbf753f35,0xbe95bf35,0xbf7f3f0e,0xbdc9bf55,0x3f463e48,0xbf223f7b,
0x3f223ec4,0xbf463f6d,0x3dc9bf6d,0x3f7fbec4,0x3e95bf7b,0x3f75be48,0xbf623f55,0xbef1bf0e,0xbf0e3f80,0xbf558000,0x3f550000,0xbf0e3f80,
0x3f7bbec4,0xbe483f6d,0x3e48bf6d,0x3f7bbec4,0xbe48bf35,0x3f7bbf35,0xbf7b3f35,0xbe48bf35,0xbf553f6d,0xbf0ebec4,0x3f0e3ec4,0xbf553f6d,
0x3f22bf80,0x3f468000,0xbdc9bf35,0x3f7fbf35,0xbf623e48,0x3ef1bf7b,0xbf753f55,0xbe95bf0e,0xbe953f6d,0xbf753ec4,0x3ef13ec4,0xbf623f6d,
0x3f7fbf0e,0xbdc93f55,0x3f46bf7b,0x3f223e48,0xbf353f80,0xbf358000,0xbf353f80,0xbf358000,0x3f350000,0xbf353f80,0x3f350000,0xbf353f80,
0x3f35bf80,0x3f358000,0x3f35bf80,0x3f358000,0xbf350000,0x3f35bf80,0xbf350000,0x3f35bf80,0x3f46bf80,0x3f228000,0x3f7fbf35,0xbdc93f35,
0xbef1be48,0x3f62bf7b,0x3e95bf55,0x3f75bf0e,0xbf753f6d,0xbe95bec4,0xbf623ec4,0x3ef1bf6d,0x3dc93f0e,0xbf7f3f55,0xbf223f7b,0xbf463e48,
0xbf553f80,0xbf0e8000,0xbf0e0000,0x3f55bf80,0x3e483ec4,0xbf7b3f6d,0xbf7b3f6d,0xbe48bec4,0x3f7bbf35,0xbe483f35,0xbe483f35,0xbf7b3f35,
0x3f0ebf6d,0x3f55bec4,0x3f55bec4,0xbf0e3f6d,0x3f62bf80,0x3ef18000,0xbe953f35,0xbf753f35,0x3dc9bf0e,0x3f7fbf55,0x3f22be48,0xbf463f7b,
0xbf463ec4,0x3f22bf6d,0x3f7fbf6d,0x3dc93ec4,0xbf753f7b,0xbe95be48,0x3ef1bf55,0x3f62bf0e,0xbf6d3f80,0xbec48000,0x3f6dbf80,0x3ec48000,
0xbec43f35,0xbf6d3f35,0x3ec4bf35,0x3f6dbf35,0x3ec40000,0xbf6d3f80,0xbec40000,0x3f6dbf80,0x3f6dbf35,0xbec43f35,0xbf6d3f35,0x3ec4bf35,
0x3f75bf80,0x3e958000,0xbf623f35,0x3ef1bf35,0x3f22bf55,0x3f46bf0e,0xbf7f3f7b,0xbdc9be48,0x3dc9bec4,0x3f7fbf6d,0xbf463f6d,0xbf223ec4,
0xbef13e48,0x3f62bf7b,0xbe953f0e,0xbf753f55,0xbf7b3f80,0xbe488000,0x3e480000,0xbf7b3f80,0xbf553f6d,0xbf0e3ec4,0x3f0ebec4,0xbf553f6d,
0xbf0e3f35,0xbf553f35,0x3f55bf35,0xbf0e3f35,0xbe483ec4,0xbf7b3f6d,0x3f7bbf6d,0xbe483ec4,0x3f7fbf80,0x3dc98000,0x3f22bf35,0x3f46bf35,
0x3f75bf7b,0x3e95be48,0x3ef1bf0e,0x3f62bf55,0x3f62bf6d,0x3ef1bec4,0x3e95bec4,0x3f75bf6d,0x3f46bf55,0x3f22bf0e,0x3dc9be48,0x3f7fbf7b,
0x3f803f80,0xbf803f80,0x3f803f80,0xbf803f80,0x3f803f80,0xbf803f80,0x3f803f80,0xbf803f80,0x3f803f80,0xbf803f80,0x3f803f80,0xbf803f80,
0x3f803f80,0xbf803f80,0x3f803f80,0xbf803f80,0x3dc90000,0x3f7f3f80,0x3f463f35,0x3f223f35,0x3e953e48,0x3f753f7b,0x3f623f55,0x3ef13f0e,
0x3ef13ec4,0x3f623f6d,0x3f753f6d,0x3e953ec4,0x3f223f0e,0x3f463f55,0x3f7f3f7b,0x3dc93e48,0xbf7bbf80,0x3e488000,0x3e480000,0x3f7b3f80,
0xbf55bf6d,0x3f0e3ec4,0x3f0e3ec4,0x3f553f6d,0xbf0ebf35,0x3f553f35,0x3f553f35,0x3f0e3f35,0xbe48bec4,0x3f7b3f6d,0x3f7b3f6d,0x3e483ec4,
0xbe950000,0xbf75bf80,0xbef1bf35,0x3f623f35,0xbf46bf0e,0xbf22bf55,0x3dc9be48,0x3f7f3f7b,0xbf7fbf6d,0xbdc9bec4,0x3f223ec4,0x3f463f6d,
0xbf62bf7b,0x3ef13e48,0x3f753f55,0x3e953f0e,0x3f6d3f80,0xbec48000,0xbf6dbf80,0x3ec48000,0x3ec43f35,0xbf6dbf35,0xbec4bf35,0x3f6d3f35,
0xbec40000,0xbf6dbf80,0x3ec40000,0x3f6d3f80,0xbf6dbf35,0xbec4bf35,0x3f6d3f35,0x3ec43f35,0x3ef10000,0x3f623f80,0xbf75bf35,0xbe95bf35,
0x3f7f3f55,0x3dc93f0e,0xbf46bf7b,0x3f223e48,0x3f223f6d,0xbf46bec4,0x3dc9bec4,0x3f7f3f6d,0xbe953e48,0xbf75bf7b,0x3f623f0e,0x3ef13f55,
0xbf55bf80,0x3f0e8000,0xbf0e0000,0xbf55bf80,0x3e48bec4,0x3f7b3f6d,0xbf7bbf6d,0x3e48bec4,0x3f7b3f35,0x3e483f35,0xbe48bf35,0x3f7b3f35,
0x3f0e3f6d,0xbf55bec4,0x3f553ec4,0x3f0e3f6d,0xbf220000,0xbf46bf80,0x3dc93f35,0xbf7fbf35,0xbf62bf7b,0x3ef1be48,0xbf75bf0e,0xbe95bf55,
0x3e95bec4,0x3f753f6d,0xbef1bf6d,0x3f623ec4,0x3f7f3f55,0xbdc93f0e,0x3f463e48,0x3f223f7b,0x3f353f80,0xbf358000,0x3f353f80,0xbf358000,
0xbf350000,0xbf35bf80,0xbf350000,0xbf35bf80,0xbf35bf80,0x3f358000,0xbf35bf80,0x3f358000,0x3f350000,0x3f353f80,0x3f350000,0x3f353f80,
0x3f460000,0x3f223f80,0x3f7f3f35,0xbdc93f35,0x3ef13f7b,0xbf62be48,0xbe953f0e,0xbf75bf55,0xbf75bec4,0xbe95bf6d,0xbf62bf6d,0x3ef1bec4,
0xbdc9bf55,0x3f7f3f0e,0x3f22be48,0x3f463f7b,0xbf0ebf80,0x3f558000,0x3f550000,0x3f0e3f80,0x3f7b3ec4,0x3e483f6d,0x3e483f6d,0xbf7bbec4,
0xbe483f35,0xbf7bbf35,0xbf7bbf35,0x3e48bf35,0xbf55bf6d,0x3f0ebec4,0x3f0ebec4,0x3f553f6d,0xbf620000,0xbef1bf80,0x3e95bf35,0x3f753f35,
0x3dc9bf55,0x3f7f3f0e,0x3f223f7b,0xbf463e48,0x3f463f6d,0xbf223ec4,0xbf7fbec4,0xbdc9bf6d,0xbf75be48,0xbe95bf7b,0x3ef1bf0e,0x3f623f55,
0x3ec43f80,0xbf6d8000,0xbec4bf80,0x3f6d8000,0xbf6dbf35,0x3ec4bf35,0x3f6d3f35,0xbec43f35,0x3f6d0000,0x3ec43f80,0xbf6d0000,0xbec4bf80,
0xbec43f35,0xbf6dbf35,0x3ec4bf35,0x3f6d3f35,0x3f750000,0x3e953f80,0xbf62bf35,0x3ef1bf35,0xbf223f0e,0xbf46bf55,0x3f7f3e48,0x3dc93f7b,
0x3dc9bf6d,0x3f7f3ec4,0xbf463ec4,0xbf22bf6d,0x3ef13f7b,0xbf623e48,0x3e95bf55,0x3f753f0e,0xbe48bf80,0x3f7b8000,0xbf7b0000,0xbe48bf80,
0x3f0e3f6d,0xbf553ec4,0x3f55bec4,0x3f0e3f6d,0xbf55bf35,0x3f0ebf35,0xbf0e3f35,0xbf55bf35,0x3f7b3ec4,0xbe483f6d,0x3e48bf6d,0x3f7b3ec4,
0xbf7f0000,0xbdc9bf80,0xbf223f35,0xbf46bf35,0x3f75be48,0x3e953f7b,0x3ef1bf55,0x3f623f0e,0xbf623ec4,0xbef1bf6d,0xbe953f6d,0xbf75bec4,
0x3f46bf0e,0x3f223f55,0x3dc9bf7b,0x3f7f3e48,0x3f80,0xbf808000,0x3f80,0xbf808000,0xbf80,0x3f808000,0xbf80,0x3f808000,
0x3f80,0xbf808000,0x3f80,0xbf808000,0xbf80,0x3f808000,0xbf80,0x3f808000,0x3f7f0000,0xbdc93f80,0x3f223f35,0xbf463f35,
0xbf75be48,0x3e95bf7b,0xbef1bf55,0x3f62bf0e,0x3f623ec4,0xbef13f6d,0x3e953f6d,0xbf753ec4,0xbf46bf0e,0x3f22bf55,0xbdc9bf7b,0x3f7fbe48,
0x3e48bf80,0x3f7b8000,0x3f7b0000,0xbe483f80,0xbf0e3f6d,0xbf55bec4,0xbf55bec4,0x3f0ebf6d,0x3f55bf35,0x3f0e3f35,0x3f0e3f35,0xbf553f35,
0xbf7b3ec4,0xbe48bf6d,0xbe48bf6d,0x3f7bbec4,0xbf750000,0x3e95bf80,0x3f62bf35,0x3ef13f35,0x3f223f0e,0xbf463f55,0xbf7f3e48,0x3dc9bf7b,
0xbdc9bf6d,0x3f7fbec4,0x3f463ec4,0xbf223f6d,0xbef13f7b,0xbf62be48,0xbe95bf55,0x3f75bf0e,0xbec43f80,0xbf6d8000,0x3ec4bf80,0x3f6d8000,
0x3f6dbf35,0x3ec43f35,0xbf6d3f35,0xbec4bf35,0xbf6d0000,0x3ec4bf80,0x3f6d0000,0xbec43f80,0x3ec43f35,0xbf6d3f35,0xbec4bf35,0x3f6dbf35,
0x3f620000,0xbef13f80,0xbe95bf35,0x3f75bf35,0xbdc9bf55,0x3f7fbf0e,0xbf223f7b,0xbf46be48,0xbf463f6d,0xbf22bec4,0x3f7fbec4,0xbdc93f6d,
0x3f75be48,0xbe953f7b,0xbef1bf0e,0x3f62bf55,0x3f0ebf80,0x3f558000,0xbf550000,0x3f0ebf80,0xbf7b3ec4,0x3e48bf6d,0xbe483f6d,0xbf7b3ec4,
0x3e483f35,0xbf7b3f35,0x3f7bbf35,0x3e483f35,0x3f55bf6d,0x3f0e3ec4,0xbf0ebec4,0x3f55bf6d,0xbf460000,0x3f22bf80,0xbf7f3f35,0xbdc9bf35,
0xbef13f7b,0xbf623e48,0x3e953f0e,0xbf753f55,0x3f75bec4,0xbe953f6d,0x3f62bf6d,0x3ef13ec4,0x3dc9bf55,0x3f7fbf0e,0xbf22be48,0x3f46bf7b,
0xbf353f80,0xbf358000,0xbf353f80,0xbf358000,0x3f350000,0xbf353f80,0x3f350000,0xbf353f80,0x3f35bf80,0x3f358000,0x3f35bf80,0x3f358000,
0xbf350000,0x3f35bf80,0xbf350000,0x3f35bf80,0x3f220000,0xbf463f80,0xbdc93f35,0xbf7f3f35,0x3f62bf7b,0x3ef13e48,0x3f75bf0e,0xbe953f55,
0xbe95bec4,0x3f75bf6d,0x3ef1bf6d,0x3f62bec4,0xbf7f3f55,0xbdc9bf0e,0xbf463e48,0x3f22bf7b,0x3f55bf80,0x3f0e8000,0x3f0e0000,0xbf553f80,
0xbe48bec4,0x3f7bbf6d,0x3f7bbf6d,0x3e483ec4,0xbf7b3f35,0x3e48bf35,0x3e48bf35,0x3f7bbf35,0xbf0e3f6d,0xbf553ec4,0xbf553ec4,0x3f0ebf6d,
0xbef10000,0x3f62bf80,0x3f75bf35,0xbe953f35,0xbf7f3f55,0x3dc9bf0e,0x3f46bf7b,0x3f22be48,0xbf223f6d,0xbf463ec4,0xbdc9bec4,0x3f7fbf6d,
0x3e953e48,0xbf753f7b,0xbf623f0e,0x3ef1bf55,0xbf6d3f80,0xbec48000,0x3f6dbf80,0x3ec48000,0xbec43f35,0xbf6d3f35,0x3ec4bf35,0x3f6dbf35,
0x3ec40000,0xbf6d3f80,0xbec40000,0x3f6dbf80,0x3f6dbf35,0xbec43f35,0xbf6d3f35,0x3ec4bf35,0x3e950000,0xbf753f80,0x3ef1bf35,0x3f62bf35,
0x3f46bf0e,0xbf223f55,0xbdc9be48,0x3f7fbf7b,0x3f7fbf6d,0xbdc93ec4,0xbf223ec4,0x3f46bf6d,0x3f62bf7b,0x3ef1be48,0xbf753f55,0x3e95bf0e,
0x3f7bbf80,0x3e488000,0xbe480000,0x3f7bbf80,0x3f55bf6d,0x3f0ebec4,0xbf0e3ec4,0x3f55bf6d,0x3f0ebf35,0x3f55bf35,0xbf553f35,0x3f0ebf35,
0x3e48bec4,0x3f7bbf6d,0xbf7b3f6d,0x3e48bec4,0xbdc90000,0x3f7fbf80,0xbf463f35,0x3f22bf35,0xbe953e48,0x3f75bf7b,0xbf623f55,0x3ef1bf0e,
0xbef13ec4,0x3f62bf6d,0xbf753f6d,0x3e95bec4,0xbf223f0e,0x3f46bf55,0xbf7f3f7b,0x3dc9be48,0x3f803f80,0xbf353f35,0x3f803f80,0xbf353f35,
0x3f803f80,0xbf353f35,0x3f803f80,0xbf353f35,0x3f803f80,0xbf353f35,0x3f803f80,0xbf353f35,0x3f803f80,0xbf353f35,0x3f803f80,0xbf353f35,
0x3f7e3f80,0xbdfbbcc9,0x3f1d3f31,0xbf4abf39,0x3f733f7a,0xbea1be60,0x3ee63f09,0xbf65bf58,0x3f5f3f6a,0xbefcbecf,0x3e893eb8,0xbf77bf6f,
0x3f423f51,0xbf27bf13,0x3d973e2f,0xbf7fbf7c,0x3f783f80,0xbe79bd49,0xbe79bd49,0xbf78bf80,0x3f4e3f67,0xbf18bedb,0xbf18bedb,0xbf4ebf67,
0x3f043f2c,0xbf5cbf3e,0xbf5cbf3e,0xbf04bf2c,0x3e163eac,0xbf7dbf71,0xbf7dbf71,0xbe16beac,0x3f6f3f7f,0xbeb8bd97,0xbf6abf42,0xbecfbf27,
0x3f133f4a,0xbf51bf1d,0xbf7cbf7e,0x3e2fbdfb,0x3cc93ea1,0xbf80bf73,0xbf39bf65,0x3f313ee6,0xbf09be89,0xbf58bf77,0xbe60befc,0x3f7a3f5f,
0x3f623f7f,0xbef1bdc9,0xbf62bf7f,0x3ef13dc9,0x3e953f22,0xbf75bf46,0xbe95bf22,0x3f753f46,0xbef1bdc9,0xbf62bf7f,0x3ef13dc9,0x3f623f7f,
0xbf75bf46,0xbe95bf22,0x3f753f46,0x3e953f22,0x3f513f7e,0xbf13bdfb,0xbe2fbf1d,0x3f7c3f4a,0xbcc93ee6,0xbf80bf65,0x3f393ea1,0x3f313f73,
0xbf58befc,0xbf09bf5f,0x3f7a3f77,0xbe603e89,0xbf6abf7f,0x3ecfbd97,0x3eb83f42,0xbf6fbf27,0x3f3e3f7d,0xbf2cbe16,0x3f2c3e16,0x3f3e3f7d,
0xbeac3e79,0xbf71bf78,0x3f713f78,0xbeac3e79,0xbf80bf4e,0xbd49bf18,0x3d493f18,0xbf80bf4e,0xbedbbf5c,0x3f673f04,0xbf67bf04,0xbedbbf5c,
0x3f273f7c,0xbf42be2f,0x3f7f3f51,0xbd973f13,0xbf1d3cc9,0xbf4abf80,0x3dfb3f39,0xbf7ebf31,0xbf65bf7a,0x3ee6be60,0xbf73bf09,0xbea1bf58,
0x3e89becf,0x3f773f6a,0xbefcbf6f,0x3f5f3eb8,0x3f0e3f7b,0xbf55be48,0x3f0e3f7b,0xbf55be48,0xbf55be48,0xbf0ebf7b,0xbf55be48,0xbf0ebf7b,
0xbf0ebf7b,0x3f553e48,0xbf0ebf7b,0x3f553e48,0x3f553e48,0x3f0e3f7b,0x3f553e48,0x3f0e3f7b,0x3ee63f7a,0xbf65be60,0xbea13f09,0xbf73bf58,
0xbf77becf,0xbe89bf6a,0xbf5fbf6f,0x3efcbeb8,0xbd97bf51,0x3f7f3f13,0x3f27be2f,0x3f423f7c,0x3f7e3f39,0xbdfb3f31,0x3f1d3f80,0xbf4abcc9,
0x3eac3f78,0xbf71be79,0xbf71be79,0xbeacbf78,0xbf80bf18,0x3d49bf4e,0x3d49bf4e,0x3f803f18,0x3edbbf04,0x3f673f5c,0x3f673f5c,0xbedb3f04,
0x3f2c3f7d,0xbf3e3e16,0xbf3e3e16,0xbf2cbf7d,0x3e603f77,0xbf7abe89,0xbf58bf5f,0x3f09befc,0xbf6fbf42,0x3eb8bf27,0x3f6a3d97,0x3ecf3f7f,
0x3f51bdfb,0x3f133f7e,0xbe2f3f4a,0xbf7cbf1d,0x3cc93f65,0xbf80bee6,0xbf39bf73,0x3f31bea1,0x3dc93f75,0xbf7fbe95,0xbdc9bf75,0x3f7f3e95,
0xbf46bf62,0x3f22bef1,0x3f463f62,0xbf223ef1,0x3f7f3e95,0x3dc93f75,0xbf7fbe95,0xbdc9bf75,0xbf223ef1,0xbf46bf62,0x3f22bef1,0x3f463f62,
0xbcc93f73,0xbf80bea1,0x3f39bee6,0x3f313f65,0xbf09bf77,0x3f58be89,0xbe603f5f,0xbf7abefc,0x3f6a3f27,0xbecf3f42,0xbeb8bf7f,0x3f6fbd97,
0xbf7cbdfb,0xbe2fbf7e,0x3f513f4a,0xbf133f1d,0xbe163f71,0xbf7dbeac,0x3f7d3eac,0xbe163f71,0xbe79bf80,0x3f78bd49,0xbf783d49,0xbe79bf80,
0x3f183f67,0xbf4e3edb,0x3f4ebedb,0x3f183f67,0xbf5cbf2c,0x3f04bf3e,0xbf043f3e,0xbf5cbf2c,0xbe893f6f,0xbf77beb8,0x3efc3f6a,0xbf5f3ecf,
0x3d97bf7c,0x3f7f3e2f,0xbf27bf51,0x3f42bf13,0x3dfb3f80,0xbf7e3cc9,0x3f4a3f31,0xbf1d3f39,0xbea1bf7a,0x3f73be60,0xbf65bf09,0x3ee6bf58,
0xbec43f6d,0xbf6dbec4,0xbec43f6d,0xbf6dbec4,0x3ec4bf6d,0x3f6d3ec4,0x3ec4bf6d,0x3f6d3ec4,0xbec43f6d,0xbf6dbec4,0xbec43f6d,0xbf6dbec4,
0x3ec4bf6d,0x3f6d3ec4,0x3ec4bf6d,0x3f6d3ec4,0xbefc3f6a,0xbf5fbecf,0xbf773eb8,0xbe89bf6f,0x3f27bf51,0x3f423f13,0x3f7fbe2f,0x3d973f7c,
0xbf4a3f31,0xbf1dbf39,0xbf7ebcc9,0x3dfbbf80,0x3f65bf09,0x3ee63f58,0x3f733e60,0xbea13f7a,0xbf183f67,0xbf4ebedb,0xbf4ebedb,0x3f18bf67,
0x3f5cbf2c,0x3f043f3e,0x3f043f3e,0xbf5c3f2c,0xbf7d3eac,0xbe16bf71,0xbe16bf71,0x3f7dbeac,0x3f783d49,0xbe793f80,0xbe793f80,0xbf78bd49,
0xbf313f65,0xbf39bee6,0xbcc9bf73,0x3f80bea1,0x3f7abefc,0x3e603f5f,0xbf093f77,0xbf58be89,0xbf6fbd97,0x3eb8bf7f,0x3f6abf27,0x3ecf3f42,
0x3f133f1d,0xbf513f4a,0xbf7c3dfb,0x3e2fbf7e,0xbf463f62,0xbf22bef1,0x3f46bf62,0x3f223ef1,0x3f7fbe95,0xbdc93f75,0xbf7f3e95,0x3dc9bf75,
0xbf22bef1,0x3f46bf62,0x3f223ef1,0xbf463f62,0xbdc93f75,0xbf7f3e95,0x3dc9bf75,0x3f7fbe95,0xbf583f5f,0xbf09befc,0x3f7abe89,0xbe603f77,
0x3f6abd97,0xbecf3f7f,0xbeb8bf27,0x3f6fbf42,0xbe2fbf4a,0x3f7cbf1d,0xbf133f7e,0xbf51bdfb,0xbf393f73,0xbf31bea1,0x3f80bee6,0xbcc93f65,
0xbf673f5c,0xbedbbf04,0x3edb3f04,0xbf673f5c,0x3f3e3e16,0xbf2c3f7d,0x3f2cbf7d,0x3f3e3e16,0x3eacbf78,0x3f71be79,0xbf713e79,0x3eacbf78,
0xbf803f18,0xbd49bf4e,0x3d493f4e,0xbf803f18,0xbf733f58,0xbea1bf09,0xbee63f7a,0xbf653e60,0x3efc3eb8,0xbf5f3f6f,0x3f77becf,0xbe893f6a,
0x3f42bf7c,0x3f273e2f,0x3d97bf51,0x3f7fbf13,0xbf4a3cc9,0x3f1dbf80,0xbf7e3f39,0xbdfbbf31,0xbf7b3f55,0xbe48bf0e,0xbf7b3f55,0xbe48bf0e,
0x3e483f0e,0xbf7b3f55,0x3e483f0e,0xbf7b3f55,0x3f7bbf55,0x3e483f0e,0x3f7bbf55,0x3e483f0e,0xbe48bf0e,0x3f7bbf55,0xbe48bf0e,0x3f7bbf55,
0xbf7f3f51,0xbd97bf13,0xbf423e2f,0x3f27bf7c,0xbdfb3f39,0xbf7e3f31,0xbf4a3f80,0xbf1dbcc9,0x3f73bf09,0xbea13f58,0x3ee63e60,0xbf653f7a,
0x3efcbf6f,0x3f5fbeb8,0x3f77bf6a,0x3e893ecf,0xbf803f4e,0x3d49bf18,0x3d49bf18,0x3f80bf4e,0xbedb3f5c,0xbf673f04,0xbf673f04,0x3edbbf5c,
0x3f2cbe16,0xbf3e3f7d,0xbf3e3f7d,0xbf2c3e16,0x3f71bf78,0x3eac3e79,0x3eac3e79,0xbf713f78,0xbf7c3f4a,0x3e2fbf1d,0x3f51bf7e,0x3f13bdfb,
0xbf313f73,0xbf393ea1,0xbcc9bee6,0x3f80bf65,0x3e603e89,0xbf7a3f77,0xbf583efc,0x3f09bf5f,0x3f6fbf27,0xbeb83f42,0xbf6a3f7f,0xbecfbd97,
0xbf753f46,0x3e95bf22,0x3f75bf46,0xbe953f22,0xbf623f7f,0xbef13dc9,0x3f62bf7f,0x3ef1bdc9,0xbe953f22,0xbf753f46,0x3e95bf22,0x3f75bf46,
0x3ef1bdc9,0xbf623f7f,0xbef13dc9,0x3f62bf7f,0xbf6a3f42,0x3ecfbf27,0x3eb8bd97,0xbf6f3f7f,0xbf7c3f7e,0xbe2fbdfb,0x3f51bf1d,0xbf133f4a,
0xbf393f65,0xbf313ee6,0x3f80bf73,0xbcc93ea1,0xbe603efc,0xbf7a3f5f,0x3f58bf77,0x3f09be89,0xbf5c3f3e,0x3f04bf2c,0xbf043f2c,0xbf5c3f3e,
0xbf7d3f71,0x3e16beac,0xbe163eac,0xbf7d3f71,0xbf783f80,0xbe793d49,0x3e79bd49,0xbf783f80,0xbf4e3f67,0xbf183edb,0x3f18bedb,0xbf4e3f67,
0xbf4a3f39,0x3f1dbf31,0xbf7e3f80,0xbdfb3cc9,0xbf653f58,0x3ee6bf09,0xbf733f7a,0xbea13e60,0xbf773f6f,0x3e89beb8,0xbf5f3f6a,0xbefc3ecf,
0xbf7f3f7c,0x3d97be2f,0xbf423f51,0xbf273f13,0x3f803f80,0xbf353f35,0x3f803f80,0xbf353f35,0x3f803f80,0xbf353f35,0x3f803f80,0xbf353f35,
0x3f803f80,0xbf353f35,0x3f803f80,0xbf353f35,0x3f803f80,0xbf353f35,0x3f803f80,0xbf353f35,0xbdfbbcc9,0xbf7ebf80,0xbf4abf39,0xbf1dbf31,
0xbea1be60,0xbf73bf7a,0xbf65bf58,0xbee6bf09,0xbefcbecf,0xbf5fbf6a,0xbf77bf6f,0xbe89beb8,0xbf27bf13,0xbf42bf51,0xbf7fbf7c,0xbd97be2f,
0xbf78bf80,0x3e793d49,0x3e793d49,0x3f783f80,0xbf4ebf67,0x3f183edb,0x3f183edb,0x3f4e3f67,0xbf04bf2c,0x3f5c3f3e,0x3f5c3f3e,0x3f043f2c,
0xbe16beac,0x3f7d3f71,0x3f7d3f71,0x3e163eac,0x3eb83d97,0x3f6f3f7f,0x3ecf3f27,0xbf6abf42,0x3f513f1d,0x3f133f4a,0xbe2f3dfb,0xbf7cbf7e,
0x3f803f73,0x3cc93ea1,0xbf31bee6,0xbf39bf65,0x3f583f77,0xbf09be89,0xbf7abf5f,0xbe60befc,0x3f623f7f,0xbef1bdc9,0xbf62bf7f,0x3ef13dc9,
0x3e953f22,0xbf75bf46,0xbe95bf22,0x3f753f46,0xbef1bdc9,0xbf62bf7f,0x3ef13dc9,0x3f623f7f,0xbf75bf46,0xbe95bf22,0x3f753f46,0x3e953f22,
0xbf13bdfb,0xbf51bf7e,0x3f7c3f4a,0x3e2f3f1d,0xbf80bf65,0x3cc9bee6,0x3f313f73,0xbf39bea1,0xbf09bf5f,0x3f583efc,0xbe603e89,0xbf7abf77,
0x3ecfbd97,0x3f6a3f7f,0xbf6fbf27,0xbeb8bf42,0xbf3ebf7d,0x3f2c3e16,0xbf2cbe16,0xbf3ebf7d,0x3eacbe79,0x3f713f78,0xbf71bf78,0x3eacbe79,
0x3f803f4e,0x3d493f18,0xbd49bf18,0x3f803f4e,0x3edb3f5c,0xbf67bf04,0x3f673f04,0x3edb3f5c,0x3f423e2f,0x3f273f7c,0x3d97bf13,0x3f7f3f51,
0x3f4a3f80,0xbf1d3cc9,0x3f7e3f31,0x3dfb3f39,0xbee63e60,0xbf65bf7a,0x3ea13f58,0xbf73bf09,0xbf77bf6a,0x3e89becf,0xbf5fbeb8,0xbefcbf6f,
0x3f0e3f7b,0xbf55be48,0x3f0e3f7b,0xbf55be48,0xbf55be48,0xbf0ebf7b,0xbf55be48,0xbf0ebf7b,0xbf0ebf7b,0x3f553e48,0xbf0ebf7b,0x3f553e48,
0x3f553e48,0x3f0e3f7b,0x3f553e48,0x3f0e3f7b,0xbf65be60,0xbee6bf7a,0xbf73bf58,0x3ea1bf09,0xbe89bf6a,0x3f773ecf,0x3efcbeb8,0x3f5f3f6f,
0x3f7f3f13,0x3d973f51,0x3f423f7c,0xbf273e2f,0xbdfb3f31,0xbf7ebf39,0xbf4abcc9,0xbf1dbf80,0xbeacbf78,0x3f713e79,0x3f713e79,0x3eac3f78,
0x3f803f18,0xbd493f4e,0xbd493f4e,0xbf80bf18,0xbedb3f04,0xbf67bf5c,0xbf67bf5c,0x3edbbf04,0xbf2cbf7d,0x3f3ebe16,0x3f3ebe16,0x3f2c3f7d,
0x3f7a3e89,0x3e603f77,0xbf093efc,0xbf58bf5f,0xbeb83f27,0xbf6fbf42,0xbecfbf7f,0x3f6a3d97,0xbf13bf7e,0x3f51bdfb,0x3f7c3f1d,0xbe2f3f4a,
0x3f803ee6,0x3cc93f65,0xbf313ea1,0xbf39bf73,0x3dc93f75,0xbf7fbe95,0xbdc9bf75,0x3f7f3e95,0xbf46bf62,0x3f22bef1,0x3f463f62,0xbf223ef1,
0x3f7f3e95,0x3dc93f75,0xbf7fbe95,0xbdc9bf75,0xbf223ef1,0xbf46bf62,0x3f22bef1,0x3f463f62,0xbf80bea1,0x3cc9bf73,0x3f313f65,0xbf393ee6,
0x3f58be89,0x3f093f77,0xbf7abefc,0x3e60bf5f,0xbecf3f42,0xbf6abf27,0x3f6fbd97,0x3eb83f7f,0xbe2fbf7e,0x3f7c3dfb,0xbf133f1d,0xbf51bf4a,
0x3e16bf71,0x3f7d3eac,0xbf7dbeac,0x3e16bf71,0x3e793f80,0xbf783d49,0x3f78bd49,0x3e793f80,0xbf18bf67,0x3f4ebedb,0xbf4e3edb,0xbf18bf67,
0x3f5c3f2c,0xbf043f3e,0x3f04bf3e,0x3f5c3f2c,0x3f773eb8,0xbe893f6f,0x3f5fbecf,0x3efc3f6a,0xbf7fbe2f,0x3d97bf7c,0xbf423f13,0xbf27bf51,
0x3f7ebcc9,0x3dfb3f80,0x3f1dbf39,0x3f4a3f31,0xbf733e60,0xbea1bf7a,0xbee63f58,0xbf65bf09,0xbec43f6d,0xbf6dbec4,0xbec43f6d,0xbf6dbec4,
0x3ec4bf6d,0x3f6d3ec4,0x3ec4bf6d,0x3f6d3ec4,0xbec43f6d,0xbf6dbec4,0xbec43f6d,0xbf6dbec4,0x3ec4bf6d,0x3f6d3ec4,0x3ec4bf6d,0x3f6d3ec4,
0xbf5fbecf,0x3efcbf6a,0xbe89bf6f,0x3f77beb8,0x3f423f13,0xbf273f51,0x3d973f7c,0xbf7f3e2f,0xbf1dbf39,0x3f4abf31,0x3dfbbf80,0x3f7e3cc9,
0x3ee63f58,0xbf653f09,0xbea13f7a,0xbf73be60,0x3f18bf67,0x3f4e3edb,0x3f4e3edb,0xbf183f67,0xbf5c3f2c,0xbf04bf3e,0xbf04bf3e,0x3f5cbf2c,
0x3f7dbeac,0x3e163f71,0x3e163f71,0xbf7d3eac,0xbf78bd49,0x3e79bf80,0x3e79bf80,0x3f783d49,0x3f393ee6,0xbf313f65,0xbf803ea1,0xbcc9bf73,
0xbe60bf5f,0x3f7abefc,0x3f583e89,0xbf093f77,0xbeb83f7f,0xbf6fbd97,0xbecfbf42,0x3f6abf27,0x3f51bf4a,0x3f133f1d,0xbe2f3f7e,0xbf7c3dfb,
0xbf463f62,0xbf22bef1,0x3f46bf62,0x3f223ef1,0x3f7fbe95,0xbdc93f75,0xbf7f3e95,0x3dc9bf75,0xbf22bef1,0x3f46bf62,0x3f223ef1,0xbf463f62,
0xbdc93f75,0xbf7f3e95,0x3dc9bf75,0x3f7fbe95,0xbf09befc,0x3f58bf5f,0xbe603f77,0xbf7a3e89,0xbecf3f7f,0xbf6a3d97,0x3f6fbf42,0x3eb83f27,
0x3f7cbf1d,0x3e2f3f4a,0xbf51bdfb,0x3f13bf7e,0xbf31bea1,0x3f39bf73,0xbcc93f65,0xbf803ee6,0x3f67bf5c,0x3edb3f04,0xbedbbf04,0x3f67bf5c,
0xbf3ebe16,0x3f2cbf7d,0xbf2c3f7d,0xbf3ebe16,0xbeac3f78,0xbf713e79,0x3f71be79,0xbeac3f78,0x3f80bf18,0x3d493f4e,0xbd49bf4e,0x3f80bf18,
0x3ea13f09,0xbf733f58,0x3f65be60,0xbee63f7a,0x3f5fbf6f,0x3efc3eb8,0x3e89bf6a,0x3f77becf,0xbf27be2f,0x3f42bf7c,0xbf7f3f13,0x3d97bf51,
0xbf1d3f80,0xbf4a3cc9,0x3dfb3f31,0xbf7e3f39,0xbf7b3f55,0xbe48bf0e,0xbf7b3f55,0xbe48bf0e,0x3e483f0e,0xbf7b3f55,0x3e483f0e,0xbf7b3f55,
0x3f7bbf55,0x3e483f0e,0x3f7bbf55,0x3e483f0e,0xbe48bf0e,0x3f7bbf55,0xbe48bf0e,0x3f7bbf55,0xbd97bf13,0x3f7fbf51,0x3f27bf7c,0x3f42be2f,
0xbf7e3f31,0x3dfbbf39,0xbf1dbcc9,0x3f4abf80,0xbea13f58,0xbf733f09,0xbf653f7a,0xbee6be60,0x3f5fbeb8,0xbefc3f6f,0x3e893ecf,0xbf773f6a,
0x3f80bf4e,0xbd493f18,0xbd493f18,0xbf803f4e,0x3edbbf5c,0x3f67bf04,0x3f67bf04,0xbedb3f5c,0xbf2c3e16,0x3f3ebf7d,0x3f3ebf7d,0x3f2cbe16,
0xbf713f78,0xbeacbe79,0xbeacbe79,0x3f71bf78,0xbe2f3f1d,0xbf7c3f4a,0xbf133dfb,0x3f51bf7e,0x3f39bea1,0xbf313f73,0xbf803f65,0xbcc9bee6,
0x3f7abf77,0x3e603e89,0xbf093f5f,0xbf583efc,0x3eb8bf42,0x3f6fbf27,0x3ecf3d97,0xbf6a3f7f,0xbf753f46,0x3e95bf22,0x3f75bf46,0xbe953f22,
0xbf623f7f,0xbef13dc9,0x3f62bf7f,0x3ef1bdc9,0xbe953f22,0xbf753f46,0x3e95bf22,0x3f75bf46,0x3ef1bdc9,0xbf623f7f,0xbef13dc9,0x3f62bf7f,
0x3ecfbf27,0x3f6abf42,0xbf6f3f7f,0xbeb83d97,0xbe2fbdfb,0x3f7cbf7e,0xbf133f4a,0xbf513f1d,0xbf313ee6,0x3f39bf65,0xbcc93ea1,0xbf803f73,
0xbf7a3f5f,0x3e60befc,0x3f09be89,0xbf583f77,0x3f5cbf3e,0xbf043f2c,0x3f04bf2c,0x3f5cbf3e,0x3f7dbf71,0xbe163eac,0x3e16beac,0x3f7dbf71,
0x3f78bf80,0x3e79bd49,0xbe793d49,0x3f78bf80,0x3f4ebf67,0x3f18bedb,0xbf183edb,0x3f4ebf67,0xbf1d3f31,0xbf4a3f39,0x3dfbbcc9,0xbf7e3f80,
0xbee63f09,0xbf653f58,0x3ea1be60,0xbf733f7a,0xbe893eb8,0xbf773f6f,0x3efcbecf,0xbf5f3f6a,0xbd973e2f,0xbf7f3f7c,0x3f27bf13,0xbf423f51,
0x3f803f80,0xbf353f35,0x3f803f80,0xbf353f35,0x3f803f80,0xbf353f35,0x3f803f80,0xbf353f35,0x3f803f80,0xbf353f35,0x3f803f80,0xbf353f35,
0x3f803f80,0xbf353f35,0x3f803f80,0xbf353f35,0xbf7ebf80,0x3dfb3cc9,0xbf1dbf31,0x3f4a3f39,0xbf73bf7a,0x3ea13e60,0xbee6bf09,0x3f653f58,
0xbf5fbf6a,0x3efc3ecf,0xbe89beb8,0x3f773f6f,0xbf42bf51,0x3f273f13,0xbd97be2f,0x3f7f3f7c,0x3f783f80,0xbe79bd49,0xbe79bd49,0xbf78bf80,
0x3f4e3f67,0xbf18bedb,0xbf18bedb,0xbf4ebf67,0x3f043f2c,0xbf5cbf3e,0xbf5cbf3e,0xbf04bf2c,0x3e163eac,0xbf7dbf71,0xbf7dbf71,0xbe16beac,
0xbf6fbf7f,0x3eb83d97,0x3f6a3f42,0x3ecf3f27,0xbf13bf4a,0x3f513f1d,0x3f7c3f7e,0xbe2f3dfb,0xbcc9bea1,0x3f803f73,0x3f393f65,0xbf31bee6,
0x3f093e89,0x3f583f77,0x3e603efc,0xbf7abf5f,0x3f623f7f,0xbef1bdc9,0xbf62bf7f,0x3ef13dc9,0x3e953f22,0xbf75bf46,0xbe95bf22,0x3f753f46,
0xbef1bdc9,0xbf62bf7f,0x3ef13dc9,0x3f623f7f,0xbf75bf46,0xbe95bf22,0x3f753f46,0x3e953f22,0xbf51bf7e,0x3f133dfb,0x3e2f3f1d,0xbf7cbf4a,
0x3cc9bee6,0x3f803f65,0xbf39bea1,0xbf31bf73,0x3f583efc,0x3f093f5f,0xbf7abf77,0x3e60be89,0x3f6a3f7f,0xbecf3d97,0xbeb8bf42,0x3f6f3f27,
0x3f3e3f7d,0xbf2cbe16,0x3f2c3e16,0x3f3e3f7d,0xbeac3e79,0xbf71bf78,0x3f713f78,0xbeac3e79,0xbf80bf4e,0xbd49bf18,0x3d493f18,0xbf80bf4e,
0xbedbbf5c,0x3f673f04,0xbf67bf04,0xbedbbf5c,0xbf27bf7c,0x3f423e2f,0xbf7fbf51,0x3d97bf13,0x3f1dbcc9,0x3f4a3f80,0xbdfbbf39,0x3f7e3f31,
0x3f653f7a,0xbee63e60,0x3f733f09,0x3ea13f58,0xbe893ecf,0xbf77bf6a,0x3efc3f6f,0xbf5fbeb8,0x3f0e3f7b,0xbf55be48,0x3f0e3f7b,0xbf55be48,
0xbf55be48,0xbf0ebf7b,0xbf55be48,0xbf0ebf7b,0xbf0ebf7b,0x3f553e48,0xbf0ebf7b,0x3f553e48,0x3f553e48,0x3f0e3f7b,0x3f553e48,0x3f0e3f7b,
0xbee6bf7a,0x3f653e60,0x3ea1bf09,0x3f733f58,0x3f773ecf,0x3e893f6a,0x3f5f3f6f,0xbefc3eb8,0x3d973f51,0xbf7fbf13,0xbf273e2f,0xbf42bf7c,
0xbf7ebf39,0x3dfbbf31,0xbf1dbf80,0x3f4a3cc9,0x3eac3f78,0xbf71be79,0xbf71be79,0xbeacbf78,0xbf80bf18,0x3d49bf4e,0x3d49bf4e,0x3f803f18,
0x3edbbf04,0x3f673f5c,0x3f673f5c,0xbedb3f04,0x3f2c3f7d,0xbf3e3e16,0xbf3e3e16,0xbf2cbf7d,0xbe60bf77,0x3f7a3e89,0x3f583f5f,0xbf093efc,
0x3f6f3f42,0xbeb83f27,0xbf6abd97,0xbecfbf7f,0xbf513dfb,0xbf13bf7e,0x3e2fbf4a,0x3f7c3f1d,0xbcc9bf65,0x3f803ee6,0x3f393f73,0xbf313ea1,
0x3dc93f75,0xbf7fbe95,0xbdc9bf75,0x3f7f3e95,0xbf46bf62,0x3f22bef1,0x3f463f62,0xbf223ef1,0x3f7f3e95,0x3dc93f75,0xbf7fbe95,0xbdc9bf75,
0xbf223ef1,0xbf46bf62,0x3f22bef1,0x3f463f62,0x3cc9bf73,0x3f803ea1,0xbf393ee6,0xbf31bf65,0x3f093f77,0xbf583e89,0x3e60bf5f,0x3f7a3efc,
0xbf6abf27,0x3ecfbf42,0x3eb83f7f,0xbf6f3d97,0x3f7c3dfb,0x3e2f3f7e,0xbf51bf4a,0x3f13bf1d,0xbe163f71,0xbf7dbeac,0x3f7d3eac,0xbe163f71,
0xbe79bf80,0x3f78bd49,0xbf783d49,0xbe79bf80,0x3f183f67,0xbf4e3edb,0x3f4ebedb,0x3f183f67,0xbf5cbf2c,0x3f04bf3e,0xbf043f3e,0xbf5cbf2c,
0x3e89bf6f,0x3f773eb8,0xbefcbf6a,0x3f5fbecf,0xbd973f7c,0xbf7fbe2f,0x3f273f51,0xbf423f13,0xbdfbbf80,0x3f7ebcc9,0xbf4abf31,0x3f1dbf39,
0x3ea13f7a,0xbf733e60,0x3f653f09,0xbee63f58,0xbec43f6d,0xbf6dbec4,0xbec43f6d,0xbf6dbec4,0x3ec4bf6d,0x3f6d3ec4,0x3ec4bf6d,0x3f6d3ec4,
0xbec43f6d,0xbf6dbec4,0xbec43f6d,0xbf6dbec4,0x3ec4bf6d,0x3f6d3ec4,0x3ec4bf6d,0x3f6d3ec4,0x3efcbf6a,0x3f5f3ecf,0x3f77beb8,0x3e893f6f,
0xbf273f51,0xbf42bf13,0xbf7f3e2f,0xbd97bf7c,0x3f4abf31,0x3f1d3f39,0x3f7e3cc9,0xbdfb3f80,0xbf653f09,0xbee6bf58,0xbf73be60,0x3ea1bf7a,
0xbf183f67,0xbf4ebedb,0xbf4ebedb,0x3f18bf67,0x3f5cbf2c,0x3f043f3e,0x3f043f3e,0xbf5c3f2c,0xbf7d3eac,0xbe16bf71,0xbe16bf71,0x3f7dbeac,
0x3f783d49,0xbe793f80,0xbe793f80,0xbf78bd49,0x3f31bf65,0x3f393ee6,0x3cc93f73,0xbf803ea1,0xbf7a3efc,0xbe60bf5f,0x3f09bf77,0x3f583e89,
0x3f6f3d97,0xbeb83f7f,0xbf6a3f27,0xbecfbf42,0xbf13bf1d,0x3f51bf4a,0x3f7cbdfb,0xbe2f3f7e,0xbf463f62,0xbf22bef1,0x3f46bf62,0x3f223ef1,
0x3f7fbe95,0xbdc93f75,0xbf7f3e95,0x3dc9bf75,0xbf22bef1,0x3f46bf62,0x3f223ef1,0xbf463f62,0xbdc93f75,0xbf7f3e95,0x3dc9bf75,0x3f7fbe95,
0x3f58bf5f,0x3f093efc,0xbf7a3e89,0x3e60bf77,0xbf6a3d97,0x3ecfbf7f,0x3eb83f27,0xbf6f3f42,0x3e2f3f4a,0xbf7c3f1d,0x3f13bf7e,0x3f513dfb,
0x3f39bf73,0x3f313ea1,0xbf803ee6,0x3cc9bf65,0xbf673f5c,0xbedbbf04,0x3edb3f04,0xbf673f5c,0x3f3e3e16,0xbf2c3f7d,0x3f2cbf7d,0x3f3e3e16,
0x3eacbf78,0x3f71be79,0xbf713e79,0x3eacbf78,0xbf803f18,0xbd49bf4e,0x3d493f4e,0xbf803f18,0x3f73bf58,0x3ea13f09,0x3ee6bf7a,0x3f65be60,
0xbefcbeb8,0x3f5fbf6f,0xbf773ecf,0x3e89bf6a,0xbf423f7c,0xbf27be2f,0xbd973f51,0xbf7f3f13,0x3f4abcc9,0xbf1d3f80,0x3f7ebf39,0x3dfb3f31,
0xbf7b3f55,0xbe48bf0e,0xbf7b3f55,0xbe48bf0e,0x3e483f0e,0xbf7b3f55,0x3e483f0e,0xbf7b3f55,0x3f7bbf55,0x3e483f0e,0x3f7bbf55,0x3e483f0e,
0xbe48bf0e,0x3f7bbf55,0xbe48bf0e,0x3f7bbf55,0x3f7fbf51,0x3d973f13,0x3f42be2f,0xbf273f7c,0x3dfbbf39,0x3f7ebf31,0x3f4abf80,0x3f1d3cc9,
0xbf733f09,0x3ea1bf58,0xbee6be60,0x3f65bf7a,0xbefc3f6f,0xbf5f3eb8,0xbf773f6a,0xbe89becf,0xbf803f4e,0x3d49bf18,0x3d49bf18,0x3f80bf4e,
0xbedb3f5c,0xbf673f04,0xbf673f04,0x3edbbf5c,0x3f2cbe16,0xbf3e3f7d,0xbf3e3f7d,0xbf2c3e16,0x3f71bf78,0x3eac3e79,0x3eac3e79,0xbf713f78,
0x3f7cbf4a,0xbe2f3f1d,0xbf513f7e,0xbf133dfb,0x3f31bf73,0x3f39bea1,0x3cc93ee6,0xbf803f65,0xbe60be89,0x3f7abf77,0x3f58befc,0xbf093f5f,
0xbf6f3f27,0x3eb8bf42,0x3f6abf7f,0x3ecf3d97,0xbf753f46,0x3e95bf22,0x3f75bf46,0xbe953f22,0xbf623f7f,0xbef13dc9,0x3f62bf7f,0x3ef1bdc9,
0xbe953f22,0xbf753f46,0x3e95bf22,0x3f75bf46,0x3ef1bdc9,0xbf623f7f,0xbef13dc9,0x3f62bf7f,0x3f6abf42,0xbecf3f27,0xbeb83d97,0x3f6fbf7f,
0x3f7cbf7e,0x3e2f3dfb,0xbf513f1d,0x3f13bf4a,0x3f39bf65,0x3f31bee6,0xbf803f73,0x3cc9bea1,0x3e60befc,0x3f7abf5f,0xbf583f77,0xbf093e89,
0xbf5c3f3e,0x3f04bf2c,0xbf043f2c,0xbf5c3f3e,0xbf7d3f71,0x3e16beac,0xbe163eac,0xbf7d3f71,0xbf783f80,0xbe793d49,0x3e79bd49,0xbf783f80,
0xbf4e3f67,0xbf183edb,0x3f18bedb,0xbf4e3f67,0x3f4abf39,0xbf1d3f31,0x3f7ebf80,0x3dfbbcc9,0x3f65bf58,0xbee63f09,0x3f73bf7a,0x3ea1be60,
0x3f77bf6f,0xbe893eb8,0x3f5fbf6a,0x3efcbecf,0x3f7fbf7c,0xbd973e2f,0x3f42bf51,0x3f27bf13,0x3f803f80,0xbf353f35,0x3f803f80,0xbf353f35,
0x3f803f80,0xbf353f35,0x3f803f80,0xbf353f35,0x3f803f80,0xbf353f35,0x3f803f80,0xbf353f35,0x3f803f80,0xbf353f35,0x3f803f80,0xbf353f35,
0x3dfb3cc9,0x3f7e3f80,0x3f4a3f39,0x3f1d3f31,0x3ea13e60,0x3f733f7a,0x3f653f58,0x3ee63f09,0x3efc3ecf,0x3f5f3f6a,0x3f773f6f,0x3e893eb8,
0x3f273f13,0x3f423f51,0x3f7f3f7c,0x3d973e2f,0xbf78bf80,0x3e793d49,0x3e793d49,0x3f783f80,0xbf4ebf67,0x3f183edb,0x3f183edb,0x3f4e3f67,
0xbf04bf2c,0x3f5c3f3e,0x3f5c3f3e,0x3f043f2c,0xbe16beac,0x3f7d3f71,0x3f7d3f71,0x3e163eac,0xbeb8bd97,0xbf6fbf7f,0xbecfbf27,0x3f6a3f42,
0xbf51bf1d,0xbf13bf4a,0x3e2fbdfb,0x3f7c3f7e,0xbf80bf73,0xbcc9bea1,0x3f313ee6,0x3f393f65,0xbf58bf77,0x3f093e89,0x3f7a3f5f,0x3e603efc,
0x3f623f7f,0xbef1bdc9,0xbf62bf7f,0x3ef13dc9,0x3e953f22,0xbf75bf46,0xbe95bf22,0x3f753f46,0xbef1bdc9,0xbf62bf7f,0x3ef13dc9,0x3f623f7f,
0xbf75bf46,0xbe95bf22,0x3f753f46,0x3e953f22,0x3f133dfb,0x3f513f7e,0xbf7cbf4a,0xbe2fbf1d,0x3f803f65,0xbcc93ee6,0xbf31bf73,0x3f393ea1,
0x3f093f5f,0xbf58befc,0x3e60be89,0x3f7a3f77,0xbecf3d97,0xbf6abf7f,0x3f6f3f27,0x3eb83f42,0xbf3ebf7d,0x3f2c3e16,0xbf2cbe16,0xbf3ebf7d,
0x3eacbe79,0x3f713f78,0xbf71bf78,0x3eacbe79,0x3f803f4e,0x3d493f18,0xbd49bf18,0x3f803f4e,0x3edb3f5c,0xbf67bf04,0x3f673f04,0x3edb3f5c,
0xbf42be2f,0xbf27bf7c,0xbd973f13,0xbf7fbf51,0xbf4abf80,0x3f1dbcc9,0xbf7ebf31,0xbdfbbf39,0x3ee6be60,0x3f653f7a,0xbea1bf58,0x3f733f09,
0x3f773f6a,0xbe893ecf,0x3f5f3eb8,0x3efc3f6f,0x3f0e3f7b,0xbf55be48,0x3f0e3f7b,0xbf55be48,0xbf55be48,0xbf0ebf7b,0xbf55be48,0xbf0ebf7b,
0xbf0ebf7b,0x3f553e48,0xbf0ebf7b,0x3f553e48,0x3f553e48,0x3f0e3f7b,0x3f553e48,0x3f0e3f7b,0x3f653e60,0x3ee63f7a,0x3f733f58,0xbea13f09,
0x3e893f6a,0xbf77becf,0xbefc3eb8,0xbf5fbf6f,0xbf7fbf13,0xbd97bf51,0xbf42bf7c,0x3f27be2f,0x3dfbbf31,0x3f7e3f39,0x3f4a3cc9,0x3f1d3f80,
0xbeacbf78,0x3f713e79,0x3f713e79,0x3eac3f78,0x3f803f18,0xbd493f4e,0xbd493f4e,0xbf80bf18,0xbedb3f04,0xbf67bf5c,0xbf67bf5c,0x3edbbf04,
0xbf2cbf7d,0x3f3ebe16,0x3f3ebe16,0x3f2c3f7d,0xbf7abe89,0xbe60bf77,0x3f09befc,0x3f583f5f,0x3eb8bf27,0x3f6f3f42,0x3ecf3f7f,0xbf6abd97,
0x3f133f7e,0xbf513dfb,0xbf7cbf1d,0x3e2fbf4a,0xbf80bee6,0xbcc9bf65,0x3f31bea1,0x3f393f73,0x3dc93f75,0xbf7fbe95,0xbdc9bf75,0x3f7f3e95,
0xbf46bf62,0x3f22bef1,0x3f463f62,0xbf223ef1,0x3f7f3e95,0x3dc93f75,0xbf7fbe95,0xbdc9bf75,0xbf223ef1,0xbf46bf62,0x3f22bef1,0x3f463f62,
0x3f803ea1,0xbcc93f73,0xbf31bf65,0x3f39bee6,0xbf583e89,0xbf09bf77,0x3f7a3efc,0xbe603f5f,0x3ecfbf42,0x3f6a3f27,0xbf6f3d97,0xbeb8bf7f,
0x3e2f3f7e,0xbf7cbdfb,0x3f13bf1d,0x3f513f4a,0x3e16bf71,0x3f7d3eac,0xbf7dbeac,0x3e16bf71,0x3e793f80,0xbf783d49,0x3f78bd49,0x3e793f80,
0xbf18bf67,0x3f4ebedb,0xbf4e3edb,0xbf18bf67,0x3f5c3f2c,0xbf043f3e,0x3f04bf3e,0x3f5c3f2c,0xbf77beb8,0x3e89bf6f,0xbf5f3ecf,0xbefcbf6a,
0x3f7f3e2f,0xbd973f7c,0x3f42bf13,0x3f273f51,0xbf7e3cc9,0xbdfbbf80,0xbf1d3f39,0xbf4abf31,0x3f73be60,0x3ea13f7a,0x3ee6bf58,0x3f653f09,
0xbec43f6d,0xbf6dbec4,0xbec43f6d,0xbf6dbec4,0x3ec4bf6d,0x3f6d3ec4,0x3ec4bf6d,0x3f6d3ec4,0xbec43f6d,0xbf6dbec4,0xbec43f6d,0xbf6dbec4,
0x3ec4bf6d,0x3f6d3ec4,0x3ec4bf6d,0x3f6d3ec4,0x3f5f3ecf,0xbefc3f6a,0x3e893f6f,0xbf773eb8,0xbf42bf13,0x3f27bf51,0xbd97bf7c,0x3f7fbe2f,
0x3f1d3f39,0xbf4a3f31,0xbdfb3f80,0xbf7ebcc9,0xbee6bf58,0x3f65bf09,0x3ea1bf7a,0x3f733e60,0x3f18bf67,0x3f4e3edb,0x3f4e3edb,0xbf183f67,
0xbf5c3f2c,0xbf04bf3e,0xbf04bf3e,0x3f5cbf2c,0x3f7dbeac,0x3e163f71,0x3e163f71,0xbf7d3eac,0xbf78bd49,0x3e79bf80,0x3e79bf80,0x3f783d49,
0xbf39bee6,0x3f31bf65,0x3f80bea1,0x3cc93f73,0x3e603f5f,0xbf7a3efc,0xbf58be89,0x3f09bf77,0x3eb8bf7f,0x3f6f3d97,0x3ecf3f42,0xbf6a3f27,
0xbf513f4a,0xbf13bf1d,0x3e2fbf7e,0x3f7cbdfb,0xbf463f62,0xbf22bef1,0x3f46bf62,0x3f223ef1,0x3f7fbe95,0xbdc93f75,0xbf7f3e95,0x3dc9bf75,
0xbf22bef1,0x3f46bf62,0x3f223ef1,0xbf463f62,0xbdc93f75,0xbf7f3e95,0x3dc9bf75,0x3f7fbe95,0x3f093efc,0xbf583f5f,0x3e60bf77,0x3f7abe89,
0x3ecfbf7f,0x3f6abd97,0xbf6f3f42,0xbeb8bf27,0xbf7c3f1d,0xbe2fbf4a,0x3f513dfb,0xbf133f7e,0x3f313ea1,0xbf393f73,0x3cc9bf65,0x3f80bee6,
0x3f67bf5c,0x3edb3f04,0xbedbbf04,0x3f67bf5c,0xbf3ebe16,0x3f2cbf7d,0xbf2c3f7d,0xbf3ebe16,0xbeac3f78,0xbf713e79,0x3f71be79,0xbeac3f78,
0x3f80bf18,0x3d493f4e,0xbd49bf4e,0x3f80bf18,0xbea1bf09,0x3f73bf58,0xbf653e60,0x3ee6bf7a,0xbf5f3f6f,0xbefcbeb8,0xbe893f6a,0xbf773ecf,
0x3f273e2f,0xbf423f7c,0x3f7fbf13,0xbd973f51,0x3f1dbf80,0x3f4abcc9,0xbdfbbf31,0x3f7ebf39,0xbf7b3f55,0xbe48bf0e,0xbf7b3f55,0xbe48bf0e,
0x3e483f0e,0xbf7b3f55,0x3e483f0e,0xbf7b3f55,0x3f7bbf55,0x3e483f0e,0x3f7bbf55,0x3e483f0e,0xbe48bf0e,0x3f7bbf55,0xbe48bf0e,0x3f7bbf55,
0x3d973f13,0xbf7f3f51,0xbf273f7c,0xbf423e2f,0x3f7ebf31,0xbdfb3f39,0x3f1d3cc9,0xbf4a3f80,0x3ea1bf58,0x3f73bf09,0x3f65bf7a,0x3ee63e60,
0xbf5f3eb8,0x3efcbf6f,0xbe89becf,0x3f77bf6a,0x3f80bf4e,0xbd493f18,0xbd493f18,0xbf803f4e,0x3edbbf5c,0x3f67bf04,0x3f67bf04,0xbedb3f5c,
0xbf2c3e16,0x3f3ebf7d,0x3f3ebf7d,0x3f2cbe16,0xbf713f78,0xbeacbe79,0xbeacbe79,0x3f71bf78,0x3e2fbf1d,0x3f7cbf4a,0x3f13bdfb,0xbf513f7e,
0xbf393ea1,0x3f31bf73,0x3f80bf65,0x3cc93ee6,0xbf7a3f77,0xbe60be89,0x3f09bf5f,0x3f58befc,0xbeb83f42,0xbf6f3f27,0xbecfbd97,0x3f6abf7f,
0xbf753f46,0x3e95bf22,0x3f75bf46,0xbe953f22,0xbf623f7f,0xbef13dc9,0x3f62bf7f,0x3ef1bdc9,0xbe953f22,0xbf753f46,0x3e95bf22,0x3f75bf46,
0x3ef1bdc9,0xbf623f7f,0xbef13dc9,0x3f62bf7f,0xbecf3f27,0xbf6a3f42,0x3f6fbf7f,0x3eb8bd97,0x3e2f3dfb,0xbf7c3f7e,0x3f13bf4a,0x3f51bf1d,
0x3f31bee6,0xbf393f65,0x3cc9bea1,0x3f80bf73,0x3f7abf5f,0xbe603efc,0xbf093e89,0x3f58bf77,0x3f5cbf3e,0xbf043f2c,0x3f04bf2c,0x3f5cbf3e,
0x3f7dbf71,0xbe163eac,0x3e16beac,0x3f7dbf71,0x3f78bf80,0x3e79bd49,0xbe793d49,0x3f78bf80,0x3f4ebf67,0x3f18bedb,0xbf183edb,0x3f4ebf67,
0x3f1dbf31,0x3f4abf39,0xbdfb3cc9,0x3f7ebf80,0x3ee6bf09,0x3f65bf58,0xbea13e60,0x3f73bf7a,0x3e89beb8,0x3f77bf6f,0xbefc3ecf,0x3f5fbf6a,
0x3d97be2f,0x3f7fbf7c,0xbf273f13,0x3f42bf51,0x3f803f80,0xbf803f80,0x3f803f80,0xbf803f80,0x3f803f80,0xbf803f80,0x3f803f80,0xbf803f80,
0x3f803f80,0xbf803f80,0x3f803f80,0xbf803f80,0x3f803f80,0xbf803f80,0x3f803f80,0xbf803f80,0x3f7d3f80,0xbe16bd49,0x3f183f2c,0xbf4ebf3e,
0x3f713f78,0xbeacbe79,0x3edb3f04,0xbf67bf5c,0x3f5c3f67,0xbf04bedb,0x3e793eac,0xbf78bf71,0x3f3e3f4e,0xbf2cbf18,0x3d493e16,0xbf80bf7d,
0x3f753f7f,0xbe95bdc9,0xbe95bdc9,0xbf75bf7f,0x3f463f62,0xbf22bef1,0xbf22bef1,0xbf46bf62,0x3ef13f22,0xbf62bf46,0xbf62bf46,0xbef1bf22,
0x3dc93e95,0xbf7fbf75,0xbf7fbf75,0xbdc9be95,0x3f673f7d,0xbedbbe16,0xbf71bf4e,0xbeacbf18,0x3f043f3e,0xbf5cbf2c,0xbf78bf80,0x3e79bd49,
0xbd493e79,0xbf80bf78,0xbf2cbf5c,0x3f3e3f04,0xbf18beac,0xbf4ebf71,0xbe16bedb,0x3f7d3f67,0x3f553f7b,0xbf0ebe48,0xbf55bf7b,0x3f0e3e48,
0x3e483f0e,0xbf7bbf55,0xbe48bf0e,0x3f7b3f55,0xbf0ebe48,0xbf55bf7b,0x3f0e3e48,0x3f553f7b,0xbf7bbf55,0xbe48bf0e,0x3f7b3f55,0x3e483f0e,
0x3f3e3f78,0xbf2cbe79,0xbd49bf04,0x3f803f5c,0xbe163eac,0xbf7dbf71,0x3f4e3edb,0x3f183f67,0xbf67bf18,0xbedbbf4e,0x3f713f7d,0xbeac3e16,
0xbf5cbf80,0x3f043d49,0x3e793f2c,0xbf78bf3e,0x3f223f75,0xbf46be95,0x3f463e95,0x3f223f75,0xbef13dc9,0xbf62bf7f,0x3f623f7f,0xbef13dc9,
0xbf7fbf62,0x3dc9bef1,0xbdc93ef1,0xbf7fbf62,0xbe95bf46,0x3f753f22,0xbf75bf22,0xbe95bf46,0x3f043f71,0xbf5cbeac,0x3f783f67,0xbe793edb,
0xbf3ebe16,0xbf2cbf7d,0xbd493f18,0xbf80bf4e,0xbf4ebf80,0x3f18bd49,0xbf7dbf2c,0xbe16bf3e,0x3edbbe79,0x3f673f78,0xbeacbf5c,0x3f713f04,
0x3ec43f6d,0xbf6dbec4,0x3ec43f6d,0xbf6dbec4,0xbf6dbec4,0xbec4bf6d,0xbf6dbec4,0xbec4bf6d,0xbec4bf6d,0x3f6d3ec4,0xbec4bf6d,0x3f6d3ec4,
0x3f6d3ec4,0x3ec43f6d,0x3f6d3ec4,0x3ec43f6d,0x3e793f67,0xbf78bedb,0xbf043eac,0xbf5cbf71,0xbf80bf18,0xbd49bf4e,0xbf3ebf7d,0x3f2cbe16,
0x3e16bf2c,0x3f7d3f3e,0x3f4e3d49,0x3f183f80,0x3f713f5c,0xbeac3f04,0x3edb3f78,0xbf67be79,0x3dc93f62,0xbf7fbef1,0xbf7fbef1,0xbdc9bf62,
0xbf75bf46,0x3e95bf22,0x3e95bf22,0x3f753f46,0x3f22be95,0x3f463f75,0x3f463f75,0xbf223e95,0x3ef13f7f,0xbf62bdc9,0xbf62bdc9,0xbef1bf7f,
0xbd493f5c,0xbf80bf04,0xbf2cbf78,0x3f3ebe79,0xbf4ebf67,0x3f18bedb,0x3f7d3eac,0x3e163f71,0x3f713e16,0x3eac3f7d,0xbedb3f18,0xbf67bf4e,
0xbe793f3e,0xbf78bf2c,0xbf04bf80,0x3f5cbd49,0xbe483f55,0xbf7bbf0e,0x3e48bf55,0x3f7b3f0e,0xbf0ebf7b,0x3f55be48,0x3f0e3f7b,0xbf553e48,
0x3f7b3f0e,0xbe483f55,0xbf7bbf0e,0x3e48bf55,0xbf553e48,0xbf0ebf7b,0x3f55be48,0x3f0e3f7b,0xbeac3f4e,0xbf71bf18,0x3f67be16,0x3edb3f7d,
0xbe79bf80,0x3f783d49,0xbf043f2c,0xbf5cbf3e,0x3f3e3f5c,0xbf2c3f04,0xbd49bf78,0x3f803e79,0xbf7dbedb,0x3e16bf67,0x3f183f71,0xbf4e3eac,
0xbef13f46,0xbf62bf22,0x3f623f22,0xbef13f46,0x3dc9bf75,0x3f7f3e95,0xbf7fbe95,0x3dc9bf75,0x3e953f7f,0xbf753dc9,0x3f75bdc9,0x3e953f7f,
0xbf22bf62,0x3f46bef1,0xbf463ef1,0xbf22bf62,0xbf183f3e,0xbf4ebf2c,0x3e163f80,0xbf7d3d49,0x3edbbf5c,0x3f673f04,0xbeacbf78,0x3f71be79,
0xbe793f71,0xbf78beac,0x3f043f67,0xbf5c3edb,0x3d49bf7d,0x3f803e16,0xbf2cbf4e,0x3f3ebf18,0xbf353f35,0xbf35bf35,0xbf353f35,0xbf35bf35,
0x3f35bf35,0x3f353f35,0x3f35bf35,0x3f353f35,0xbf353f35,0xbf35bf35,0xbf353f35,0xbf35bf35,0x3f35bf35,0x3f353f35,0x3f35bf35,0x3f353f35,
0xbf4e3f2c,0xbf18bf3e,0xbf7dbd49,0x3e16bf80,0x3f67bf04,0x3edb3f5c,0x3f713e79,0xbeac3f78,0xbf783eac,0xbe79bf71,0xbf5cbedb,0x3f04bf67,
0x3f80be16,0x3d493f7d,0x3f3e3f18,0xbf2c3f4e,0xbf623f22,0xbef1bf46,0xbef1bf46,0x3f62bf22,0x3f7fbe95,0x3dc93f75,0x3dc93f75,0xbf7f3e95,
0xbf75bdc9,0x3e95bf7f,0x3e95bf7f,0x3f753dc9,0x3f463ef1,0xbf223f62,0xbf223f62,0xbf46bef1,0xbf713f18,0xbeacbf4e,0x3edbbf7d,0x3f673e16,
0x3f78bd49,0xbe793f80,0xbf5c3f3e,0xbf04bf2c,0xbf2cbf04,0x3f3ebf5c,0x3f80be79,0xbd493f78,0x3e163f67,0xbf7d3edb,0xbf4ebeac,0x3f18bf71,
0xbf7b3f0e,0xbe48bf55,0x3f7bbf0e,0x3e483f55,0x3f553e48,0xbf0e3f7b,0xbf55be48,0x3f0ebf7b,0xbe48bf55,0x3f7bbf0e,0x3e483f55,0xbf7b3f0e,
0xbf0e3f7b,0xbf55be48,0x3f0ebf7b,0x3f553e48,0xbf803f04,0xbd49bf5c,0x3f3e3e79,0xbf2c3f78,0x3f183edb,0xbf4e3f67,0x3e16bf71,0x3f7dbeac,
0x3eacbf7d,0x3f71be16,0xbf673f4e,0xbedbbf18,0xbf783f2c,0xbe79bf3e,0x3f5c3d49,0xbf043f80,0xbf7f3ef1,0x3dc9bf62,0xbdc93f62,0xbf7f3ef1,
0x3e953f22,0xbf753f46,0x3f75bf46,0x3e953f22,0x3f46bf75,0x3f223e95,0xbf22be95,0x3f46bf75,0xbf623dc9,0x3ef1bf7f,0xbef13f7f,0xbf623dc9,
0xbf783edb,0x3e79bf67,0xbf5c3f71,0xbf04beac,0xbd493f4e,0xbf803f18,0x3f2c3e16,0xbf3e3f7d,0x3f7dbf3e,0x3e163f2c,0x3f18bf80,0x3f4ebd49,
0xbeacbf04,0x3f71bf5c,0xbf673e79,0x3edbbf78,0xbf6d3ec4,0x3ec4bf6d,0xbf6d3ec4,0x3ec4bf6d,0xbec43f6d,0xbf6d3ec4,0xbec43f6d,0xbf6d3ec4,
0x3f6dbec4,0xbec43f6d,0x3f6dbec4,0xbec43f6d,0x3ec4bf6d,0x3f6dbec4,0x3ec4bf6d,0x3f6dbec4,0xbf5c3eac,0x3f04bf71,0xbe79bedb,0x3f78bf67,
0xbf2c3f7d,0xbf3e3e16,0xbf803f4e,0xbd49bf18,0x3f183d49,0xbf4e3f80,0xbe163f3e,0xbf7d3f2c,0x3f67bf78,0x3edb3e79,0x3f71bf04,0xbeac3f5c,
0xbf463e95,0x3f22bf75,0x3f22bf75,0x3f46be95,0xbf623f7f,0xbef1bdc9,0xbef1bdc9,0x3f62bf7f,0x3dc93ef1,0xbf7f3f62,0xbf7f3f62,0xbdc9bef1,
0x3f75bf22,0xbe953f46,0xbe953f46,0xbf753f22,0xbf2c3e79,0x3f3ebf78,0x3f80bf5c,0xbd493f04,0xbf7d3f71,0xbe16beac,0x3f18bf67,0x3f4ebedb,
0xbedb3f4e,0xbf673f18,0xbeacbe16,0x3f71bf7d,0x3f04bd49,0xbf5c3f80,0xbf783f3e,0x3e79bf2c,0xbf0e3e48,0x3f55bf7b,0x3f0ebe48,0xbf553f7b,
0xbf7b3f55,0x3e48bf0e,0x3f7bbf55,0xbe483f0e,0xbf553f7b,0xbf0e3e48,0x3f55bf7b,0x3f0ebe48,0xbe483f0e,0xbf7b3f55,0x3e48bf0e,0x3f7bbf55,
0xbedb3e16,0x3f67bf7d,0xbeac3f18,0xbf713f4e,0xbf5c3f2c,0x3f04bf3e,0x3e793d49,0xbf783f80,0xbf803f78,0xbd49be79,0x3f3ebf04,0xbf2c3f5c,
0xbf4e3f71,0xbf183eac,0x3f7dbf67,0xbe163edb,0xbe953dc9,0x3f75bf7f,0xbf753f7f,0xbe953dc9,0xbf223ef1,0x3f46bf62,0xbf463f62,0xbf223ef1,
0xbf623f46,0x3ef1bf22,0xbef13f22,0xbf623f46,0xbf7f3f75,0x3dc9be95,0xbdc93e95,0xbf7f3f75,0xbe163d49,0x3f7dbf80,0xbf4e3f3e,0x3f18bf2c,
0xbeac3e79,0x3f71bf78,0xbf673f5c,0x3edbbf04,0xbf043edb,0x3f5cbf67,0xbf783f71,0x3e79beac,0xbf2c3f18,0x3f3ebf4e,0xbf803f7d,0x3d49be16,
0x3f803f80,0xbf803f80,0x3f803f80,0xbf803f80,0x3f803f80,0xbf803f80,0x3f803f80,0xbf803f80,0x3f803f80,0xbf803f80,0x3f803f80,0xbf803f80,
0x3f803f80,0xbf803f80,0x3f803f80,0xbf803f80,0xbe16bd49,0xbf7dbf80,0xbf4ebf3e,0xbf18bf2c,0xbeacbe79,0xbf71bf78,0xbf67bf5c,0xbedbbf04,
0xbf04bedb,0xbf5cbf67,0xbf78bf71,0xbe79beac,0xbf2cbf18,0xbf3ebf4e,0xbf80bf7d,0xbd49be16,0xbf75bf7f,0x3e953dc9,0x3e953dc9,0x3f753f7f,
0xbf46bf62,0x3f223ef1,0x3f223ef1,0x3f463f62,0xbef1bf22,0x3f623f46,0x3f623f46,0x3ef13f22,0xbdc9be95,0x3f7f3f75,0x3f7f3f75,0x3dc93e95,
0x3edb3e16,0x3f673f7d,0x3eac3f18,0xbf71bf4e,0x3f5c3f2c,0x3f043f3e,0xbe793d49,0xbf78bf80,0x3f803f78,0xbd493e79,0xbf3ebf04,0xbf2cbf5c,
0x3f4e3f71,0xbf18beac,0xbf7dbf67,0xbe16bedb,0x3f553f7b,0xbf0ebe48,0xbf55bf7b,0x3f0e3e48,0x3e483f0e,0xbf7bbf55,0xbe48bf0e,0x3f7b3f55,
0xbf0ebe48,0xbf55bf7b,0x3f0e3e48,0x3f553f7b,0xbf7bbf55,0xbe48bf0e,0x3f7b3f55,0x3e483f0e,0xbf2cbe79,0xbf3ebf78,0x3f803f5c,0x3d493f04,
0xbf7dbf71,0x3e16beac,0x3f183f67,0xbf4ebedb,0xbedbbf4e,0x3f673f18,0xbeac3e16,0xbf71bf7d,0x3f043d49,0x3f5c3f80,0xbf78bf3e,0xbe79bf2c,
0xbf22bf75,0x3f463e95,0xbf46be95,0xbf22bf75,0x3ef1bdc9,0x3f623f7f,0xbf62bf7f,0x3ef1bdc9,0x3f7f3f62,0xbdc93ef1,0x3dc9bef1,0x3f7f3f62,
0x3e953f46,0xbf75bf22,0x3f753f22,0x3e953f46,0x3f5c3eac,0x3f043f71,0x3e79bedb,0x3f783f67,0x3f2c3f7d,0xbf3ebe16,0x3f803f4e,0xbd493f18,
0xbf183d49,0xbf4ebf80,0x3e163f3e,0xbf7dbf2c,0xbf67bf78,0x3edbbe79,0xbf71bf04,0xbeacbf5c,0x3ec43f6d,0xbf6dbec4,0x3ec43f6d,0xbf6dbec4,
0xbf6dbec4,0xbec4bf6d,0xbf6dbec4,0xbec4bf6d,0xbec4bf6d,0x3f6d3ec4,0xbec4bf6d,0x3f6d3ec4,0x3f6d3ec4,0x3ec43f6d,0x3f6d3ec4,0x3ec43f6d,
0xbf78bedb,0xbe79bf67,0xbf5cbf71,0x3f04beac,0xbd49bf4e,0x3f803f18,0x3f2cbe16,0x3f3e3f7d,0x3f7d3f3e,0xbe163f2c,0x3f183f80,0xbf4ebd49,
0xbeac3f04,0xbf71bf5c,0xbf67be79,0xbedbbf78,0xbdc9bf62,0x3f7f3ef1,0x3f7f3ef1,0x3dc93f62,0x3f753f46,0xbe953f22,0xbe953f22,0xbf75bf46,
0xbf223e95,0xbf46bf75,0xbf46bf75,0x3f22be95,0xbef1bf7f,0x3f623dc9,0x3f623dc9,0x3ef13f7f,0x3f803f04,0xbd493f5c,0xbf3e3e79,0xbf2cbf78,
0xbf183edb,0xbf4ebf67,0xbe16bf71,0x3f7d3eac,0xbeacbf7d,0x3f713e16,0x3f673f4e,0xbedb3f18,0x3f783f2c,0xbe793f3e,0xbf5c3d49,0xbf04bf80,
0xbe483f55,0xbf7bbf0e,0x3e48bf55,0x3f7b3f0e,0xbf0ebf7b,0x3f55be48,0x3f0e3f7b,0xbf553e48,0x3f7b3f0e,0xbe483f55,0xbf7bbf0e,0x3e48bf55,
0xbf553e48,0xbf0ebf7b,0x3f55be48,0x3f0e3f7b,0xbf71bf18,0x3eacbf4e,0x3edb3f7d,0xbf673e16,0x3f783d49,0x3e793f80,0xbf5cbf3e,0x3f04bf2c,
0xbf2c3f04,0xbf3ebf5c,0x3f803e79,0x3d493f78,0x3e16bf67,0x3f7d3edb,0xbf4e3eac,0xbf18bf71,0x3ef1bf46,0x3f623f22,0xbf62bf22,0x3ef1bf46,
0xbdc93f75,0xbf7fbe95,0x3f7f3e95,0xbdc93f75,0xbe95bf7f,0x3f75bdc9,0xbf753dc9,0xbe95bf7f,0x3f223f62,0xbf463ef1,0x3f46bef1,0x3f223f62,
0x3f4e3f2c,0xbf183f3e,0x3f7dbd49,0x3e163f80,0xbf67bf04,0x3edbbf5c,0xbf713e79,0xbeacbf78,0x3f783eac,0xbe793f71,0x3f5cbedb,0x3f043f67,
0xbf80be16,0x3d49bf7d,0xbf3e3f18,0xbf2cbf4e,0xbf353f35,0xbf35bf35,0xbf353f35,0xbf35bf35,0x3f35bf35,0x3f353f35,0x3f35bf35,0x3f353f35,
0xbf353f35,0xbf35bf35,0xbf353f35,0xbf35bf35,0x3f35bf35,0x3f353f35,0x3f35bf35,0x3f353f35,0xbf18bf3e,0x3f4ebf2c,0x3e16bf80,0x3f7d3d49,
0x3edb3f5c,0xbf673f04,0xbeac3f78,0xbf71be79,0xbe79bf71,0x3f78beac,0x3f04bf67,0x3f5c3edb,0x3d493f7d,0xbf803e16,0xbf2c3f4e,0xbf3ebf18,
0x3f62bf22,0x3ef13f46,0x3ef13f46,0xbf623f22,0xbf7f3e95,0xbdc9bf75,0xbdc9bf75,0x3f7fbe95,0x3f753dc9,0xbe953f7f,0xbe953f7f,0xbf75bdc9,
0xbf46bef1,0x3f22bf62,0x3f22bf62,0x3f463ef1,0x3eac3f4e,0xbf713f18,0xbf67be16,0x3edbbf7d,0x3e79bf80,0x3f78bd49,0x3f043f2c,0xbf5c3f3e,
0xbf3e3f5c,0xbf2cbf04,0x3d49bf78,0x3f80be79,0x3f7dbedb,0x3e163f67,0xbf183f71,0xbf4ebeac,0xbf7b3f0e,0xbe48bf55,0x3f7bbf0e,0x3e483f55,
0x3f553e48,0xbf0e3f7b,0xbf55be48,0x3f0ebf7b,0xbe48bf55,0x3f7bbf0e,0x3e483f55,0xbf7b3f0e,0xbf0e3f7b,0xbf55be48,0x3f0ebf7b,0x3f553e48,
0xbd49bf5c,0x3f80bf04,0xbf2c3f78,0xbf3ebe79,0xbf4e3f67,0xbf18bedb,0x3f7dbeac,0xbe163f71,0x3f71be16,0xbeac3f7d,0xbedbbf18,0x3f67bf4e,
0xbe79bf3e,0x3f78bf2c,0xbf043f80,0xbf5cbd49,0x3f7fbef1,0xbdc93f62,0x3dc9bf62,0x3f7fbef1,0xbe95bf22,0x3f75bf46,0xbf753f46,0xbe95bf22,
0xbf463f75,0xbf22be95,0x3f223e95,0xbf463f75,0x3f62bdc9,0xbef13f7f,0x3ef1bf7f,0x3f62bdc9,0xbe793f67,0xbf783edb,0x3f043eac,0xbf5c3f71,
0x3f80bf18,0xbd493f4e,0x3f3ebf7d,0x3f2c3e16,0xbe16bf2c,0x3f7dbf3e,0xbf4e3d49,0x3f18bf80,0xbf713f5c,0xbeacbf04,0xbedb3f78,0xbf673e79,
0xbf6d3ec4,0x3ec4bf6d,0xbf6d3ec4,0x3ec4bf6d,0xbec43f6d,0xbf6d3ec4,0xbec43f6d,0xbf6d3ec4,0x3f6dbec4,0xbec43f6d,0x3f6dbec4,0xbec43f6d,
0x3ec4bf6d,0x3f6dbec4,0x3ec4bf6d,0x3f6dbec4,0x3f04bf71,0x3f5cbeac,0x3f78bf67,0x3e793edb,0xbf3e3e16,0x3f2cbf7d,0xbd49bf18,0x3f80bf4e,
0xbf4e3f80,0xbf18bd49,0xbf7d3f2c,0x3e16bf3e,0x3edb3e79,0xbf673f78,0xbeac3f5c,0xbf713f04,0x3f46be95,0xbf223f75,0xbf223f75,0xbf463e95,
0x3f62bf7f,0x3ef13dc9,0x3ef13dc9,0xbf623f7f,0xbdc9bef1,0x3f7fbf62,0x3f7fbf62,0x3dc93ef1,0xbf753f22,0x3e95bf46,0x3e95bf46,0x3f75bf22,
0xbf3e3f78,0xbf2c3e79,0x3d49bf04,0x3f80bf5c,0x3e163eac,0xbf7d3f71,0xbf4e3edb,0x3f18bf67,0x3f67bf18,0xbedb3f4e,0xbf713f7d,0xbeacbe16,
0x3f5cbf80,0x3f04bd49,0xbe793f2c,0xbf783f3e,0xbf0e3e48,0x3f55bf7b,0x3f0ebe48,0xbf553f7b,0xbf7b3f55,0x3e48bf0e,0x3f7bbf55,0xbe483f0e,
0xbf553f7b,0xbf0e3e48,0x3f55bf7b,0x3f0ebe48,0xbe483f0e,0xbf7b3f55,0x3e48bf0e,0x3f7bbf55,0x3f67bf7d,0x3edbbe16,0xbf713f4e,0x3eacbf18,
0x3f04bf3e,0x3f5cbf2c,0xbf783f80,0xbe79bd49,0xbd49be79,0x3f80bf78,0xbf2c3f5c,0xbf3e3f04,0xbf183eac,0x3f4ebf71,0xbe163edb,0xbf7d3f67,
0x3e95bdc9,0xbf753f7f,0x3f75bf7f,0x3e95bdc9,0x3f22bef1,0xbf463f62,0x3f46bf62,0x3f22bef1,0x3f62bf46,0xbef13f22,0x3ef1bf22,0x3f62bf46,
0x3f7fbf75,0xbdc93e95,0x3dc9be95,0x3f7fbf75,0xbf7d3f80,0xbe163d49,0xbf183f2c,0xbf4e3f3e,0xbf713f78,0xbeac3e79,0xbedb3f04,0xbf673f5c,
0xbf5c3f67,0xbf043edb,0xbe793eac,0xbf783f71,0xbf3e3f4e,0xbf2c3f18,0xbd493e16,0xbf803f7d,0x3f803f80,0xbf803f80,0x3f803f80,0xbf803f80,
0x3f803f80,0xbf803f80,0x3f803f80,0xbf803f80,0x3f803f80,0xbf803f80,0x3f803f80,0xbf803f80,0x3f803f80,0xbf803f80,0x3f803f80,0xbf803f80,
0xbf7dbf80,0x3e163d49,0xbf18bf2c,0x3f4e3f3e,0xbf71bf78,0x3eac3e79,0xbedbbf04,0x3f673f5c,0xbf5cbf67,0x3f043edb,0xbe79beac,0x3f783f71,
0xbf3ebf4e,0x3f2c3f18,0xbd49be16,0x3f803f7d,0x3f753f7f,0xbe95bdc9,0xbe95bdc9,0xbf75bf7f,0x3f463f62,0xbf22bef1,0xbf22bef1,0xbf46bf62,
0x3ef13f22,0xbf62bf46,0xbf62bf46,0xbef1bf22,0x3dc93e95,0xbf7fbf75,0xbf7fbf75,0xbdc9be95,0xbf67bf7d,0x3edb3e16,0x3f713f4e,0x3eac3f18,
0xbf04bf3e,0x3f5c3f2c,0x3f783f80,0xbe793d49,0x3d49be79,0x3f803f78,0x3f2c3f5c,0xbf3ebf04,0x3f183eac,0x3f4e3f71,0x3e163edb,0xbf7dbf67,
0x3f553f7b,0xbf0ebe48,0xbf55bf7b,0x3f0e3e48,0x3e483f0e,0xbf7bbf55,0xbe48bf0e,0x3f7b3f55,0xbf0ebe48,0xbf55bf7b,0x3f0e3e48,0x3f553f7b,
0xbf7bbf55,0xbe48bf0e,0x3f7b3f55,0x3e483f0e,0xbf3ebf78,0x3f2c3e79,0x3d493f04,0xbf80bf5c,0x3e16beac,0x3f7d3f71,0xbf4ebedb,0xbf18bf67,
0x3f673f18,0x3edb3f4e,0xbf71bf7d,0x3eacbe16,0x3f5c3f80,0xbf04bd49,0xbe79bf2c,0x3f783f3e,0x3f223f75,0xbf46be95,0x3f463e95,0x3f223f75,
0xbef13dc9,0xbf62bf7f,0x3f623f7f,0xbef13dc9,0xbf7fbf62,0x3dc9bef1,0xbdc93ef1,0xbf7fbf62,0xbe95bf46,0x3f753f22,0xbf75bf22,0xbe95bf46,
0xbf04bf71,0x3f5c3eac,0xbf78bf67,0x3e79bedb,0x3f3e3e16,0x3f2c3f7d,0x3d49bf18,0x3f803f4e,0x3f4e3f80,0xbf183d49,0x3f7d3f2c,0x3e163f3e,
0xbedb3e79,0xbf67bf78,0x3eac3f5c,0xbf71bf04,0x3ec43f6d,0xbf6dbec4,0x3ec43f6d,0xbf6dbec4,0xbf6dbec4,0xbec4bf6d,0xbf6dbec4,0xbec4bf6d,
0xbec4bf6d,0x3f6d3ec4,0xbec4bf6d,0x3f6d3ec4,0x3f6d3ec4,0x3ec43f6d,0x3f6d3ec4,0x3ec43f6d,0xbe79bf67,0x3f783edb,0x3f04beac,0x3f5c3f71,
0x3f803f18,0x3d493f4e,0x3f3e3f7d,0xbf2c3e16,0xbe163f2c,0xbf7dbf3e,0xbf4ebd49,0xbf18bf80,0xbf71bf5c,0x3eacbf04,0xbedbbf78,0x3f673e79,
0x3dc93f62,0xbf7fbef1,0xbf7fbef1,0xbdc9bf62,0xbf75bf46,0x3e95bf22,0x3e95bf22,0x3f753f46,0x3f22be95,0x3f463f75,0x3f463f75,0xbf223e95,
0x3ef13f7f,0xbf62bdc9,0xbf62bdc9,0xbef1bf7f,0x3d49bf5c,0x3f803f04,0x3f2c3f78,0xbf3e3e79,0x3f4e3f67,0xbf183edb,0xbf7dbeac,0xbe16bf71,
0xbf71be16,0xbeacbf7d,0x3edbbf18,0x3f673f4e,0x3e79bf3e,0x3f783f2c,0x3f043f80,0xbf5c3d49,0xbe483f55,0xbf7bbf0e,0x3e48bf55,0x3f7b3f0e,
0xbf0ebf7b,0x3f55be48,0x3f0e3f7b,0xbf553e48,0x3f7b3f0e,0xbe483f55,0xbf7bbf0e,0x3e48bf55,0xbf553e48,0xbf0ebf7b,0x3f55be48,0x3f0e3f7b,
0x3eacbf4e,0x3f713f18,0xbf673e16,0xbedbbf7d,0x3e793f80,0xbf78bd49,0x3f04bf2c,0x3f5c3f3e,0xbf3ebf5c,0x3f2cbf04,0x3d493f78,0xbf80be79,
0x3f7d3edb,0xbe163f67,0xbf18bf71,0x3f4ebeac,0xbef13f46,0xbf62bf22,0x3f623f22,0xbef13f46,0x3dc9bf75,0x3f7f3e95,0xbf7fbe95,0x3dc9bf75,
0x3e953f7f,0xbf753dc9,0x3f75bdc9,0x3e953f7f,0xbf22bf62,0x3f46bef1,0xbf463ef1,0xbf22bf62,0x3f18bf3e,0x3f4e3f2c,0xbe16bf80,0x3f7dbd49,
0xbedb3f5c,0xbf67bf04,0x3eac3f78,0xbf713e79,0x3e79bf71,0x3f783eac,0xbf04bf67,0x3f5cbedb,0xbd493f7d,0xbf80be16,0x3f2c3f4e,0xbf3e3f18,
0xbf353f35,0xbf35bf35,0xbf353f35,0xbf35bf35,0x3f35bf35,0x3f353f35,0x3f35bf35,0x3f353f35,0xbf353f35,0xbf35bf35,0xbf353f35,0xbf35bf35,
0x3f35bf35,0x3f353f35,0x3f35bf35,0x3f353f35,0x3f4ebf2c,0x3f183f3e,0x3f7d3d49,0xbe163f80,0xbf673f04,0xbedbbf5c,0xbf71be79,0x3eacbf78,
0x3f78beac,0x3e793f71,0x3f5c3edb,0xbf043f67,0xbf803e16,0xbd49bf7d,0xbf3ebf18,0x3f2cbf4e,0xbf623f22,0xbef1bf46,0xbef1bf46,0x3f62bf22,
0x3f7fbe95,0x3dc93f75,0x3dc93f75,0xbf7f3e95,0xbf75bdc9,0x3e95bf7f,0x3e95bf7f,0x3f753dc9,0x3f463ef1,0xbf223f62,0xbf223f62,0xbf46bef1,
0x3f71bf18,0x3eac3f4e,0xbedb3f7d,0xbf67be16,0xbf783d49,0x3e79bf80,0x3f5cbf3e,0x3f043f2c,0x3f2c3f04,0xbf3e3f5c,0xbf803e79,0x3d49bf78,
0xbe16bf67,0x3f7dbedb,0x3f4e3eac,0xbf183f71,0xbf7b3f0e,0xbe48bf55,0x3f7bbf0e,0x3e483f55,0x3f553e48,0xbf0e3f7b,0xbf55be48,0x3f0ebf7b,
0xbe48bf55,0x3f7bbf0e,0x3e483f55,0xbf7b3f0e,0xbf0e3f7b,0xbf55be48,0x3f0ebf7b,0x3f553e48,0x3f80bf04,0x3d493f5c,0xbf3ebe79,0x3f2cbf78,
0xbf18bedb,0x3f4ebf67,0xbe163f71,0xbf7d3eac,0xbeac3f7d,0xbf713e16,0x3f67bf4e,0x3edb3f18,0x3f78bf2c,0x3e793f3e,0xbf5cbd49,0x3f04bf80,
0xbf7f3ef1,0x3dc9bf62,0xbdc93f62,0xbf7f3ef1,0x3e953f22,0xbf753f46,0x3f75bf46,0x3e953f22,0x3f46bf75,0x3f223e95,0xbf22be95,0x3f46bf75,
0xbf623dc9,0x3ef1bf7f,0xbef13f7f,0xbf623dc9,0x3f78bedb,0xbe793f67,0x3f5cbf71,0x3f043eac,0x3d49bf4e,0x3f80bf18,0xbf2cbe16,0x3f3ebf7d,
0xbf7d3f3e,0xbe16bf2c,0xbf183f80,0xbf4e3d49,0x3eac3f04,0xbf713f5c,0x3f67be79,0xbedb3f78,0xbf6d3ec4,0x3ec4bf6d,0xbf6d3ec4,0x3ec4bf6d,
0xbec43f6d,0xbf6d3ec4,0xbec43f6d,0xbf6d3ec4,0x3f6dbec4,0xbec43f6d,0x3f6dbec4,0xbec43f6d,0x3ec4bf6d,0x3f6dbec4,0x3ec4bf6d,0x3f6dbec4,
0x3f5cbeac,0xbf043f71,0x3e793edb,0xbf783f67,0x3f2cbf7d,0x3f3ebe16,0x3f80bf4e,0x3d493f18,0xbf18bd49,0x3f4ebf80,0x3e16bf3e,0x3f7dbf2c,
0xbf673f78,0xbedbbe79,0xbf713f04,0x3eacbf5c,0xbf463e95,0x3f22bf75,0x3f22bf75,0x3f46be95,0xbf623f7f,0xbef1bdc9,0xbef1bdc9,0x3f62bf7f,
0x3dc93ef1,0xbf7f3f62,0xbf7f3f62,0xbdc9bef1,0x3f75bf22,0xbe953f46,0xbe953f46,0xbf753f22,0x3f2cbe79,0xbf3e3f78,0xbf803f5c,0x3d49bf04,
0x3f7dbf71,0x3e163eac,0xbf183f67,0xbf4e3edb,0x3edbbf4e,0x3f67bf18,0x3eac3e16,0xbf713f7d,0xbf043d49,0x3f5cbf80,0x3f78bf3e,0xbe793f2c,
0xbf0e3e48,0x3f55bf7b,0x3f0ebe48,0xbf553f7b,0xbf7b3f55,0x3e48bf0e,0x3f7bbf55,0xbe483f0e,0xbf553f7b,0xbf0e3e48,0x3f55bf7b,0x3f0ebe48,
0xbe483f0e,0xbf7b3f55,0x3e48bf0e,0x3f7bbf55,0x3edbbe16,0xbf673f7d,0x3eacbf18,0x3f71bf4e,0x3f5cbf2c,0xbf043f3e,0xbe79bd49,0x3f78bf80,
0x3f80bf78,0x3d493e79,0xbf3e3f04,0x3f2cbf5c,0x3f4ebf71,0x3f18beac,0xbf7d3f67,0x3e16bedb,0xbe953dc9,0x3f75bf7f,0xbf753f7f,0xbe953dc9,
0xbf223ef1,0x3f46bf62,0xbf463f62,0xbf223ef1,0xbf623f46,0x3ef1bf22,0xbef13f22,0xbf623f46,0xbf7f3f75,0x3dc9be95,0xbdc93e95,0xbf7f3f75,
0x3e16bd49,0xbf7d3f80,0x3f4ebf3e,0xbf183f2c,0x3eacbe79,0xbf713f78,0x3f67bf5c,0xbedb3f04,0x3f04bedb,0xbf5c3f67,0x3f78bf71,0xbe793eac,
0x3f2cbf18,0xbf3e3f4e,0x3f80bf7d,0xbd493e16,0x3f803f80,0xbf803f80,0x3f803f80,0xbf803f80,0x3f803f80,0xbf803f80,0x3f803f80,0xbf803f80,
0x3f803f80,0xbf803f80,0x3f803f80,0xbf803f80,0x3f803f80,0xbf803f80,0x3f803f80,0xbf803f80,0x3e163d49,0x3f7d3f80,0x3f4e3f3e,0x3f183f2c,
0x3eac3e79,0x3f713f78,0x3f673f5c,0x3edb3f04,0x3f043edb,0x3f5c3f67,0x3f783f71,0x3e793eac,0x3f2c3f18,0x3f3e3f4e,0x3f803f7d,0x3d493e16,
0xbf75bf7f,0x3e953dc9,0x3e953dc9,0x3f753f7f,0xbf46bf62,0x3f223ef1,0x3f223ef1,0x3f463f62,0xbef1bf22,0x3f623f46,0x3f623f46,0x3ef13f22,
0xbdc9be95,0x3f7f3f75,0x3f7f3f75,0x3dc93e95,0xbedbbe16,0xbf67bf7d,0xbeacbf18,0x3f713f4e,0xbf5cbf2c,0xbf04bf3e,0x3e79bd49,0x3f783f80,
0xbf80bf78,0x3d49be79,0x3f3e3f04,0x3f2c3f5c,0xbf4ebf71,0x3f183eac,0x3f7d3f67,0x3e163edb,0x3f553f7b,0xbf0ebe48,0xbf55bf7b,0x3f0e3e48,
0x3e483f0e,0xbf7bbf55,0xbe48bf0e,0x3f7b3f55,0xbf0ebe48,0xbf55bf7b,0x3f0e3e48,0x3f553f7b,0xbf7bbf55,0xbe48bf0e,0x3f7b3f55,0x3e483f0e,
0x3f2c3e79,0x3f3e3f78,0xbf80bf5c,0xbd49bf04,0x3f7d3f71,0xbe163eac,0xbf18bf67,0x3f4e3edb,0x3edb3f4e,0xbf67bf18,0x3eacbe16,0x3f713f7d,
0xbf04bd49,0xbf5cbf80,0x3f783f3e,0x3e793f2c,0xbf22bf75,0x3f463e95,0xbf46be95,0xbf22bf75,0x3ef1bdc9,0x3f623f7f,0xbf62bf7f,0x3ef1bdc9,
0x3f7f3f62,0xbdc93ef1,0x3dc9bef1,0x3f7f3f62,0x3e953f46,0xbf75bf22,0x3f753f22,0x3e953f46,0xbf5cbeac,0xbf04bf71,0xbe793edb,0xbf78bf67,
0xbf2cbf7d,0x3f3e3e16,0xbf80bf4e,0x3d49bf18,0x3f18bd49,0x3f4e3f80,0xbe16bf3e,0x3f7d3f2c,0x3f673f78,0xbedb3e79,0x3f713f04,0x3eac3f5c,
0x3ec43f6d,0xbf6dbec4,0x3ec43f6d,0xbf6dbec4,0xbf6dbec4,0xbec4bf6d,0xbf6dbec4,0xbec4bf6d,0xbec4bf6d,0x3f6d3ec4,0xbec4bf6d,0x3f6d3ec4,
0x3f6d3ec4,0x3ec43f6d,0x3f6d3ec4,0x3ec43f6d,0x3f783edb,0x3e793f67,0x3f5c3f71,0xbf043eac,0x3d493f4e,0xbf80bf18,0xbf2c3e16,0xbf3ebf7d,
0xbf7dbf3e,0x3e16bf2c,0xbf18bf80,0x3f4e3d49,0x3eacbf04,0x3f713f5c,0x3f673e79,0x3edb3f78,0xbdc9bf62,0x3f7f3ef1,0x3f7f3ef1,0x3dc93f62,
0x3f753f46,0xbe953f22,0xbe953f22,0xbf75bf46,0xbf223e95,0xbf46bf75,0xbf46bf75,0x3f22be95,0xbef1bf7f,0x3f623dc9,0x3f623dc9,0x3ef13f7f,
0xbf80bf04,0x3d49bf5c,0x3f3ebe79,0x3f2c3f78,0x3f18bedb,0x3f4e3f67,0x3e163f71,0xbf7dbeac,0x3eac3f7d,0xbf71be16,0xbf67bf4e,0x3edbbf18,
0xbf78bf2c,0x3e79bf3e,0x3f5cbd49,0x3f043f80,0xbe483f55,0xbf7bbf0e,0x3e48bf55,0x3f7b3f0e,0xbf0ebf7b,0x3f55be48,0x3f0e3f7b,0xbf553e48,
0x3f7b3f0e,0xbe483f55,0xbf7bbf0e,0x3e48bf55,0xbf553e48,0xbf0ebf7b,0x3f55be48,0x3f0e3f7b,0x3f713f18,0xbeac3f4e,0xbedbbf7d,0x3f67be16,
0xbf78bd49,0xbe79bf80,0x3f5c3f3e,0xbf043f2c,0x3f2cbf04,0x3f3e3f5c,0xbf80be79,0xbd49bf78,0xbe163f67,0xbf7dbedb,0x3f4ebeac,0x3f183f71,
0x3ef1bf46,0x3f623f22,0xbf62bf22,0x3ef1bf46,0xbdc93f75,0xbf7fbe95,0x3f7f3e95,0xbdc93f75,0xbe95bf7f,0x3f75bdc9,0xbf753dc9,0xbe95bf7f,
0x3f223f62,0xbf463ef1,0x3f46bef1,0x3f223f62,0xbf4ebf2c,0x3f18bf3e,0xbf7d3d49,0xbe16bf80,0x3f673f04,0xbedb3f5c,0x3f71be79,0x3eac3f78,
0xbf78beac,0x3e79bf71,0xbf5c3edb,0xbf04bf67,0x3f803e16,0xbd493f7d,0x3f3ebf18,0x3f2c3f4e,0xbf353f35,0xbf35bf35,0xbf353f35,0xbf35bf35,
0x3f35bf35,0x3f353f35,0x3f35bf35,0x3f353f35,0xbf353f35,0xbf35bf35,0xbf353f35,0xbf35bf35,0x3f35bf35,0x3f353f35,0x3f35bf35,0x3f353f35,
0x3f183f3e,0xbf4e3f2c,0xbe163f80,0xbf7dbd49,0xbedbbf5c,0x3f67bf04,0x3eacbf78,0x3f713e79,0x3e793f71,0xbf783eac,0xbf043f67,0xbf5cbedb,
0xbd49bf7d,0x3f80be16,0x3f2cbf4e,0x3f3e3f18,0x3f62bf22,0x3ef13f46,0x3ef13f46,0xbf623f22,0xbf7f3e95,0xbdc9bf75,0xbdc9bf75,0x3f7fbe95,
0x3f753dc9,0xbe953f7f,0xbe953f7f,0xbf75bdc9,0xbf46bef1,0x3f22bf62,0x3f22bf62,0x3f463ef1,0xbeacbf4e,0x3f71bf18,0x3f673e16,0xbedb3f7d,
0xbe793f80,0xbf783d49,0xbf04bf2c,0x3f5cbf3e,0x3f3ebf5c,0x3f2c3f04,0xbd493f78,0xbf803e79,0xbf7d3edb,0xbe16bf67,0x3f18bf71,0x3f4e3eac,
0xbf7b3f0e,0xbe48bf55,0x3f7bbf0e,0x3e483f55,0x3f553e48,0xbf0e3f7b,0xbf55be48,0x3f0ebf7b,0xbe48bf55,0x3f7bbf0e,0x3e483f55,0xbf7b3f0e,
0xbf0e3f7b,0xbf55be48,0x3f0ebf7b,0x3f553e48,0x3d493f5c,0xbf803f04,0x3f2cbf78,0x3f3e3e79,0x3f4ebf67,0x3f183edb,0xbf7d3eac,0x3e16bf71,
0xbf713e16,0x3eacbf7d,0x3edb3f18,0xbf673f4e,0x3e793f3e,0xbf783f2c,0x3f04bf80,0x3f5c3d49,0x3f7fbef1,0xbdc93f62,0x3dc9bf62,0x3f7fbef1,
0xbe95bf22,0x3f75bf46,0xbf753f46,0xbe95bf22,0xbf463f75,0xbf22be95,0x3f223e95,0xbf463f75,0x3f62bdc9,0xbef13f7f,0x3ef1bf7f,0x3f62bdc9,
0x3e79bf67,0x3f78bedb,0xbf04beac,0x3f5cbf71,0xbf803f18,0x3d49bf4e,0xbf3e3f7d,0xbf2cbe16,0x3e163f2c,0xbf7d3f3e,0x3f4ebd49,0xbf183f80,
0x3f71bf5c,0x3eac3f04,0x3edbbf78,0x3f67be79,0xbf6d3ec4,0x3ec4bf6d,0xbf6d3ec4,0x3ec4bf6d,0xbec43f6d,0xbf6d3ec4,0xbec43f6d,0xbf6d3ec4,
0x3f6dbec4,0xbec43f6d,0x3f6dbec4,0xbec43f6d,0x3ec4bf6d,0x3f6dbec4,0x3ec4bf6d,0x3f6dbec4,0xbf043f71,0xbf5c3eac,0xbf783f67,0xbe79bedb,
0x3f3ebe16,0xbf2c3f7d,0x3d493f18,0xbf803f4e,0x3f4ebf80,0x3f183d49,0x3f7dbf2c,0xbe163f3e,0xbedbbe79,0x3f67bf78,0x3eacbf5c,0x3f71bf04,
0x3f46be95,0xbf223f75,0xbf223f75,0xbf463e95,0x3f62bf7f,0x3ef13dc9,0x3ef13dc9,0xbf623f7f,0xbdc9bef1,0x3f7fbf62,0x3f7fbf62,0x3dc93ef1,
0xbf753f22,0x3e95bf46,0x3e95bf46,0x3f75bf22,0x3f3ebf78,0x3f2cbe79,0xbd493f04,0xbf803f5c,0xbe16beac,0x3f7dbf71,0x3f4ebedb,0xbf183f67,
0xbf673f18,0x3edbbf4e,0x3f71bf7d,0x3eac3e16,0xbf5c3f80,0xbf043d49,0x3e79bf2c,0x3f78bf3e,0xbf0e3e48,0x3f55bf7b,0x3f0ebe48,0xbf553f7b,
0xbf7b3f55,0x3e48bf0e,0x3f7bbf55,0xbe483f0e,0xbf553f7b,0xbf0e3e48,0x3f55bf7b,0x3f0ebe48,0xbe483f0e,0xbf7b3f55,0x3e48bf0e,0x3f7bbf55,
0xbf673f7d,0xbedb3e16,0x3f71bf4e,0xbeac3f18,0xbf043f3e,0xbf5c3f2c,0x3f78bf80,0x3e793d49,0x3d493e79,0xbf803f78,0x3f2cbf5c,0x3f3ebf04,
0x3f18beac,0xbf4e3f71,0x3e16bedb,0x3f7dbf67,0x3e95bdc9,0xbf753f7f,0x3f75bf7f,0x3e95bdc9,0x3f22bef1,0xbf463f62,0x3f46bf62,0x3f22bef1,
0x3f62bf46,0xbef13f22,0x3ef1bf22,0x3f62bf46,0x3f7fbf75,0xbdc93e95,0x3dc9be95,0x3f7fbf75,0x3f7dbf80,0x3e16bd49,0x3f18bf2c,0x3f4ebf3e,
0x3f71bf78,0x3eacbe79,0x3edbbf04,0x3f67bf5c,0x3f5cbf67,0x3f04bedb,0x3e79beac,0x3f78bf71,0x3f3ebf4e,0x3f2cbf18,0x3d49be16,0x3f80bf7d,
0x3f803f80,0xbf353f35,0x3f803f80,0xbf353f35,0x3f803f80,0xbf353f35,0x3f803f80,0xbf353f35,0x3f803f80,0xbf353f35,0x3f803f80,0xbf353f35,
0x3f803f80,0xbf353f35,0x3f803f80,0xbf353f35,0x3f7c3f7f,0xbe2fbd97,0x3f133f27,0xbf51bf42,0x3f6f3f77,0xbeb8be89,0x3ecf3efc,0xbf6abf5f,
0x3f583f65,0xbf09bee6,0x3e603ea1,0xbf7abf73,0x3f393f4a,0xbf31bf1d,0x3cc93dfb,0xbf80bf7e,0x3f713f7d,0xbeacbe16,0xbeacbe16,0xbf71bf7d,
0x3f3e3f5c,0xbf2cbf04,0xbf2cbf04,0xbf3ebf5c,0x3edb3f18,0xbf67bf4e,0xbf67bf4e,0xbedbbf18,0x3d493e79,0xbf80bf78,0xbf80bf78,0xbd49be79,
0x3f5f3f7a,0xbefcbe60,0xbf77bf58,0xbe89bf09,0x3ee63f31,0xbf65bf39,0xbf73bf80,0x3ea13cc9,0xbdfb3e2f,0xbf7ebf7c,0xbf1dbf51,0x3f4a3f13,
0xbf27becf,0xbf42bf6a,0xbd97beb8,0x3f7f3f6f,0x3f463f75,0xbf22be95,0xbf46bf75,0x3f223e95,0x3dc93ef1,0xbf7fbf62,0xbdc9bef1,0x3f7f3f62,
0xbf22be95,0xbf46bf75,0x3f223e95,0x3f463f75,0xbf7fbf62,0xbdc9bef1,0x3f7f3f62,0x3dc93ef1,0x3f273f6f,0xbf42beb8,0x3d97becf,0x3f7f3f6a,
0xbe893e60,0xbf77bf7a,0x3f5f3f09,0x3efc3f58,0xbf73bf31,0xbea1bf39,0x3f653f80,0xbee63cc9,0xbf4abf7c,0x3f1d3e2f,0x3dfb3f13,0xbf7ebf51,
0x3f043f67,0xbf5cbedb,0x3f5c3edb,0x3f043f67,0xbf18bd49,0xbf4ebf80,0x3f4e3f80,0xbf18bd49,0xbf78bf71,0x3e79beac,0xbe793eac,0xbf78bf71,
0xbe16bf2c,0x3f7d3f3e,0xbf7dbf3e,0xbe16bf2c,0x3eb83f5f,0xbf6fbefc,0x3f6a3f77,0xbecf3e89,0xbf58bea1,0xbf09bf73,0xbe603ee6,0xbf7abf65,
0xbf31bf7e,0x3f393dfb,0xbf80bf4a,0x3cc9bf1d,0x3f13bd97,0x3f513f7f,0xbe2fbf42,0x3f7c3f27,0x3e483f55,0xbf7bbf0e,0x3e483f55,0xbf7bbf0e,
0xbf7bbf0e,0xbe48bf55,0xbf7bbf0e,0xbe48bf55,0xbe48bf55,0x3f7b3f0e,0xbe48bf55,0x3f7b3f0e,0x3f7b3f0e,0x3e483f55,0x3f7b3f0e,0x3e483f55,
0x3cc93f4a,0xbf80bf1d,0xbf313dfb,0xbf39bf7e,0xbf7cbf42,0x3e2fbf27,0xbf13bf7f,0x3f513d97,0x3eb8befc,0x3f6f3f5f,0x3f6a3e89,0x3ecf3f77,
0x3f583f73,0xbf093ea1,0x3e603f65,0xbf7abee6,0xbe163f3e,0xbf7dbf2c,0xbf7dbf2c,0x3e16bf3e,0xbf5cbf67,0x3f04bedb,0x3f04bedb,0x3f5c3f67,
0x3f4ebd49,0x3f183f80,0x3f183f80,0xbf4e3d49,0x3e793f71,0xbf78beac,0xbf78beac,0xbe79bf71,0xbea13f31,0xbf73bf39,0xbee6bf80,0x3f653cc9,
0xbf1dbf7c,0x3f4abe2f,0x3f7e3f13,0xbdfb3f51,0x3f7f3ecf,0x3d973f6a,0xbf273eb8,0xbf42bf6f,0xbefc3f09,0xbf5fbf58,0xbe89bf7a,0x3f773e60,
0xbef13f22,0xbf62bf46,0x3ef1bf22,0x3f623f46,0xbe95bf7f,0x3f753dc9,0x3e953f7f,0xbf75bdc9,0x3f623f46,0xbef13f22,0xbf62bf46,0x3ef1bf22,
0xbf75bdc9,0xbe95bf7f,0x3f753dc9,0x3e953f7f,0xbf1d3f13,0xbf4abf51,0x3f7e3e2f,0x3dfb3f7c,0x3d97bf6f,0x3f7f3eb8,0xbf423ecf,0xbf27bf6a,
0x3efc3f7a,0xbf5f3e60,0x3e89bf58,0x3f773f09,0xbf65bf31,0x3ee6bf39,0x3ea13f80,0xbf733cc9,0xbf3e3f04,0xbf2cbf5c,0x3f2c3f5c,0xbf3e3f04,
0x3edbbf4e,0x3f673f18,0xbf67bf18,0x3edbbf4e,0xbd493f78,0xbf80be79,0x3f803e79,0xbd493f78,0xbeacbf7d,0x3f71be16,0xbf713e16,0xbeacbf7d,
0xbf583ee6,0xbf09bf65,0xbe603f73,0xbf7abea1,0x3f39bf1d,0x3f313f4a,0x3cc9bf7e,0x3f803dfb,0xbf133f42,0xbf51bf27,0x3e2f3f7f,0xbf7c3d97,
0x3ecfbf5f,0x3f6a3efc,0xbeb8bf77,0x3f6fbe89,0xbf6d3ec4,0xbec4bf6d,0xbf6d3ec4,0xbec4bf6d,0x3f6dbec4,0x3ec43f6d,0x3f6dbec4,0x3ec43f6d,
0xbf6d3ec4,0xbec4bf6d,0xbf6d3ec4,0xbec4bf6d,0x3f6dbec4,0x3ec43f6d,0x3f6dbec4,0x3ec43f6d,0xbf7a3ea1,0xbe60bf73,0xbf58bee6,0x3f09bf65,
0x3f80bdfb,0x3cc93f7e,0x3f393f1d,0xbf313f4a,0xbf7cbd97,0x3e2fbf7f,0xbf13bf42,0x3f51bf27,0x3f6f3e89,0xbeb83f77,0x3ecf3f5f,0xbf6a3efc,
0xbf803e79,0xbd49bf78,0xbd49bf78,0x3f80be79,0x3f713e16,0xbeac3f7d,0xbeac3f7d,0xbf71be16,0xbf3ebf04,0x3f2cbf5c,0x3f2cbf5c,0x3f3e3f04,
0x3edb3f4e,0xbf673f18,0xbf673f18,0xbedbbf4e,0xbf7e3e2f,0x3dfbbf7c,0x3f4abf51,0x3f1d3f13,0x3f423ecf,0xbf273f6a,0xbf7f3eb8,0xbd97bf6f,
0xbe89bf58,0x3f77bf09,0x3f5f3e60,0xbefc3f7a,0xbea13f80,0xbf73bcc9,0xbee6bf39,0x3f65bf31,0xbf753dc9,0x3e95bf7f,0x3f75bdc9,0xbe953f7f,
0x3ef13f22,0xbf623f46,0xbef1bf22,0x3f62bf46,0x3e95bf7f,0x3f75bdc9,0xbe953f7f,0xbf753dc9,0xbf623f46,0xbef1bf22,0x3f62bf46,0x3ef13f22,
0xbf653cc9,0x3ee6bf80,0x3ea13f31,0xbf733f39,0x3dfb3f51,0xbf7e3f13,0x3f1dbf7c,0x3f4a3e2f,0x3f42bf6f,0x3f273eb8,0xbf7f3ecf,0x3d97bf6a,
0xbf773e60,0x3e89bf7a,0x3efc3f09,0xbf5f3f58,0xbf4ebd49,0x3f18bf80,0xbf183f80,0xbf4ebd49,0xbe793f71,0xbf783eac,0x3f78beac,0xbe793f71,
0x3f7dbf2c,0x3e163f3e,0xbe16bf3e,0x3f7dbf2c,0xbf04bedb,0x3f5cbf67,0xbf5c3f67,0xbf04bedb,0xbf31bdfb,0x3f39bf7e,0xbf803f1d,0x3cc9bf4a,
0xbf133f7f,0xbf513d97,0x3e2f3f27,0xbf7c3f42,0x3f6abe89,0xbecf3f77,0x3f6fbf5f,0x3eb83efc,0x3e60bf65,0x3f7abee6,0xbf09bea1,0x3f58bf73,
0xbf0ebe48,0x3f55bf7b,0xbf0ebe48,0x3f55bf7b,0xbf553f7b,0xbf0ebe48,0xbf553f7b,0xbf0ebe48,0x3f0e3e48,0xbf553f7b,0x3f0e3e48,0xbf553f7b,
0x3f55bf7b,0x3f0e3e48,0x3f55bf7b,0x3f0e3e48,0xbecfbe89,0x3f6abf77,0x3eb8bf5f,0x3f6fbefc,0xbf7a3f65,0xbe60bee6,0xbf583ea1,0x3f09bf73,
0x3cc93f1d,0xbf803f4a,0xbf313f7e,0xbf393dfb,0x3f7cbf27,0xbe2f3f42,0x3f133d97,0xbf513f7f,0xbe79beac,0x3f78bf71,0x3f78bf71,0x3e793eac,
0xbf7d3f3e,0x3e16bf2c,0x3e16bf2c,0x3f7dbf3e,0xbf043f67,0xbf5c3edb,0xbf5c3edb,0x3f04bf67,0x3f18bd49,0xbf4e3f80,0xbf4e3f80,0xbf183d49,
0xbd97becf,0x3f7fbf6a,0x3f42beb8,0xbf273f6f,0xbf5f3f09,0x3efcbf58,0x3f77bf7a,0x3e893e60,0xbf653f80,0xbee6bcc9,0x3ea1bf39,0x3f73bf31,
0xbdfb3f13,0xbf7e3f51,0xbf1d3e2f,0x3f4abf7c,0x3dc9bef1,0x3f7fbf62,0xbdc93ef1,0xbf7f3f62,0xbf223e95,0x3f46bf75,0x3f22be95,0xbf463f75,
0xbf7f3f62,0x3dc9bef1,0x3f7fbf62,0xbdc93ef1,0xbf463f75,0xbf223e95,0x3f46bf75,0x3f22be95,0x3e89bf09,0x3f77bf58,0xbf5f3f7a,0xbefc3e60,
0xbea13cc9,0x3f73bf80,0xbee63f31,0xbf653f39,0xbf4a3f13,0x3f1dbf51,0x3dfb3e2f,0xbf7e3f7c,0xbf7f3f6f,0x3d97beb8,0x3f27becf,0xbf423f6a,
0x3edbbf18,0x3f67bf4e,0xbf673f4e,0x3edbbf18,0x3d49be79,0x3f80bf78,0xbf803f78,0x3d49be79,0xbeac3e16,0x3f71bf7d,0xbf713f7d,0xbeac3e16,
0xbf2c3f04,0x3f3ebf5c,0xbf3e3f5c,0xbf2c3f04,0x3f13bf27,0x3f51bf42,0xbe2f3d97,0x3f7cbf7f,0x3ecfbefc,0x3f6abf5f,0xbeb83e89,0x3f6fbf77,
0x3e60bea1,0x3f7abf73,0xbf093ee6,0x3f58bf65,0x3cc9bdfb,0x3f80bf7e,0xbf313f1d,0x3f39bf4a,0x3f803f80,0xbf353f35,0x3f803f80,0xbf353f35,
0x3f803f80,0xbf353f35,0x3f803f80,0xbf353f35,0x3f803f80,0xbf353f35,0x3f803f80,0xbf353f35,0x3f803f80,0xbf353f35,0x3f803f80,0xbf353f35,
0xbe2fbd97,0xbf7cbf7f,0xbf51bf42,0xbf13bf27,0xbeb8be89,0xbf6fbf77,0xbf6abf5f,0xbecfbefc,0xbf09bee6,0xbf58bf65,0xbf7abf73,0xbe60bea1,
0xbf31bf1d,0xbf39bf4a,0xbf80bf7e,0xbcc9bdfb,0xbf71bf7d,0x3eac3e16,0x3eac3e16,0x3f713f7d,0xbf3ebf5c,0x3f2c3f04,0x3f2c3f04,0x3f3e3f5c,
0xbedbbf18,0x3f673f4e,0x3f673f4e,0x3edb3f18,0xbd49be79,0x3f803f78,0x3f803f78,0x3d493e79,0x3efc3e60,0x3f5f3f7a,0x3e893f09,0xbf77bf58,
0x3f653f39,0x3ee63f31,0xbea1bcc9,0xbf73bf80,0x3f7e3f7c,0xbdfb3e2f,0xbf4abf13,0xbf1dbf51,0x3f423f6a,0xbf27becf,0xbf7fbf6f,0xbd97beb8,
0x3f463f75,0xbf22be95,0xbf46bf75,0x3f223e95,0x3dc93ef1,0xbf7fbf62,0xbdc9bef1,0x3f7f3f62,0xbf22be95,0xbf46bf75,0x3f223e95,0x3f463f75,
0xbf7fbf62,0xbdc9bef1,0x3f7f3f62,0x3dc93ef1,0xbf42beb8,0xbf27bf6f,0x3f7f3f6a,0xbd973ecf,0xbf77bf7a,0x3e89be60,0x3efc3f58,0xbf5fbf09,
0xbea1bf39,0x3f733f31,0xbee63cc9,0xbf65bf80,0x3f1d3e2f,0x3f4a3f7c,0xbf7ebf51,0xbdfbbf13,0xbf04bf67,0x3f5c3edb,0xbf5cbedb,0xbf04bf67,
0x3f183d49,0x3f4e3f80,0xbf4ebf80,0x3f183d49,0x3f783f71,0xbe793eac,0x3e79beac,0x3f783f71,0x3e163f2c,0xbf7dbf3e,0x3f7d3f3e,0x3e163f2c,
0x3f6f3efc,0x3eb83f5f,0x3ecfbe89,0x3f6a3f77,0x3f093f73,0xbf58bea1,0x3f7a3f65,0xbe603ee6,0xbf39bdfb,0xbf31bf7e,0xbcc93f1d,0xbf80bf4a,
0xbf51bf7f,0x3f13bd97,0xbf7cbf27,0xbe2fbf42,0x3e483f55,0xbf7bbf0e,0x3e483f55,0xbf7bbf0e,0xbf7bbf0e,0xbe48bf55,0xbf7bbf0e,0xbe48bf55,
0xbe48bf55,0x3f7b3f0e,0xbe48bf55,0x3f7b3f0e,0x3f7b3f0e,0x3e483f55,0x3f7b3f0e,0x3e483f55,0xbf80bf1d,0xbcc9bf4a,0xbf39bf7e,0x3f31bdfb,
0x3e2fbf27,0x3f7c3f42,0x3f513d97,0x3f133f7f,0x3f6f3f5f,0xbeb83efc,0x3ecf3f77,0xbf6abe89,0xbf093ea1,0xbf58bf73,0xbf7abee6,0xbe60bf65,
0x3e16bf3e,0x3f7d3f2c,0x3f7d3f2c,0xbe163f3e,0x3f5c3f67,0xbf043edb,0xbf043edb,0xbf5cbf67,0xbf4e3d49,0xbf18bf80,0xbf18bf80,0x3f4ebd49,
0xbe79bf71,0x3f783eac,0x3f783eac,0x3e793f71,0x3f733f39,0xbea13f31,0xbf65bcc9,0xbee6bf80,0xbf4a3e2f,0xbf1dbf7c,0x3dfbbf51,0x3f7e3f13,
0xbd97bf6a,0x3f7f3ecf,0x3f423f6f,0xbf273eb8,0x3f5f3f58,0xbefc3f09,0xbf77be60,0xbe89bf7a,0xbef13f22,0xbf62bf46,0x3ef1bf22,0x3f623f46,
0xbe95bf7f,0x3f753dc9,0x3e953f7f,0xbf75bdc9,0x3f623f46,0xbef13f22,0xbf62bf46,0x3ef1bf22,0xbf75bdc9,0xbe95bf7f,0x3f753dc9,0x3e953f7f,
0xbf4abf51,0x3f1dbf13,0x3dfb3f7c,0xbf7ebe2f,0x3f7f3eb8,0xbd973f6f,0xbf27bf6a,0x3f42becf,0xbf5f3e60,0xbefcbf7a,0x3f773f09,0xbe893f58,
0x3ee6bf39,0x3f653f31,0xbf733cc9,0xbea1bf80,0x3f3ebf04,0x3f2c3f5c,0xbf2cbf5c,0x3f3ebf04,0xbedb3f4e,0xbf67bf18,0x3f673f18,0xbedb3f4e,
0x3d49bf78,0x3f803e79,0xbf80be79,0x3d49bf78,0x3eac3f7d,0xbf713e16,0x3f71be16,0x3eac3f7d,0x3f093f65,0xbf583ee6,0x3f7a3ea1,0xbe603f73,
0xbf31bf4a,0x3f39bf1d,0xbf80bdfb,0x3cc9bf7e,0x3f513f27,0xbf133f42,0x3f7cbd97,0x3e2f3f7f,0xbf6abefc,0x3ecfbf5f,0xbf6f3e89,0xbeb8bf77,
0xbf6d3ec4,0xbec4bf6d,0xbf6d3ec4,0xbec4bf6d,0x3f6dbec4,0x3ec43f6d,0x3f6dbec4,0x3ec43f6d,0xbf6d3ec4,0xbec4bf6d,0xbf6d3ec4,0xbec4bf6d,
0x3f6dbec4,0x3ec43f6d,0x3f6dbec4,0x3ec43f6d,0xbe60bf73,0x3f7abea1,0x3f09bf65,0x3f583ee6,0x3cc93f7e,0xbf803dfb,0xbf313f4a,0xbf39bf1d,
0x3e2fbf7f,0x3f7c3d97,0x3f51bf27,0x3f133f42,0xbeb83f77,0xbf6fbe89,0xbf6a3efc,0xbecfbf5f,0x3f80be79,0x3d493f78,0x3d493f78,0xbf803e79,
0xbf71be16,0x3eacbf7d,0x3eacbf7d,0x3f713e16,0x3f3e3f04,0xbf2c3f5c,0xbf2c3f5c,0xbf3ebf04,0xbedbbf4e,0x3f67bf18,0x3f67bf18,0x3edb3f4e,
0xbdfb3f7c,0xbf7e3e2f,0xbf1dbf13,0x3f4abf51,0x3f27bf6a,0x3f423ecf,0x3d973f6f,0xbf7f3eb8,0xbf773f09,0xbe89bf58,0x3efcbf7a,0x3f5f3e60,
0x3f733cc9,0xbea13f80,0xbf653f31,0xbee6bf39,0xbf753dc9,0x3e95bf7f,0x3f75bdc9,0xbe953f7f,0x3ef13f22,0xbf623f46,0xbef1bf22,0x3f62bf46,
0x3e95bf7f,0x3f75bdc9,0xbe953f7f,0xbf753dc9,0xbf623f46,0xbef1bf22,0x3f62bf46,0x3ef13f22,0x3ee6bf80,0x3f65bcc9,0xbf733f39,0xbea1bf31,
0xbf7e3f13,0xbdfbbf51,0x3f4a3e2f,0xbf1d3f7c,0x3f273eb8,0xbf423f6f,0x3d97bf6a,0x3f7fbecf,0x3e89bf7a,0x3f77be60,0xbf5f3f58,0xbefcbf09,
0x3f4e3d49,0xbf183f80,0x3f18bf80,0x3f4e3d49,0x3e79bf71,0x3f78beac,0xbf783eac,0x3e79bf71,0xbf7d3f2c,0xbe16bf3e,0x3e163f3e,0xbf7d3f2c,
0x3f043edb,0xbf5c3f67,0x3f5cbf67,0x3f043edb,0xbf393f7e,0xbf31bdfb,0xbcc93f4a,0xbf803f1d,0x3f51bd97,0xbf133f7f,0x3f7cbf42,0x3e2f3f27,
0x3ecfbf77,0x3f6abe89,0xbeb8befc,0x3f6fbf5f,0xbf7a3ee6,0x3e60bf65,0xbf583f73,0xbf09bea1,0xbf0ebe48,0x3f55bf7b,0xbf0ebe48,0x3f55bf7b,
0xbf553f7b,0xbf0ebe48,0xbf553f7b,0xbf0ebe48,0x3f0e3e48,0xbf553f7b,0x3f0e3e48,0xbf553f7b,0x3f55bf7b,0x3f0e3e48,0x3f55bf7b,0x3f0e3e48,
0x3f6abf77,0x3ecf3e89,0x3f6fbefc,0xbeb83f5f,0xbe60bee6,0x3f7abf65,0x3f09bf73,0x3f58bea1,0xbf803f4a,0xbcc9bf1d,0xbf393dfb,0x3f31bf7e,
0xbe2f3f42,0xbf7c3f27,0xbf513f7f,0xbf13bd97,0x3e793eac,0xbf783f71,0xbf783f71,0xbe79beac,0x3f7dbf3e,0xbe163f2c,0xbe163f2c,0xbf7d3f3e,
0x3f04bf67,0x3f5cbedb,0x3f5cbedb,0xbf043f67,0xbf183d49,0x3f4ebf80,0x3f4ebf80,0x3f18bd49,0xbf7f3f6a,0xbd97becf,0x3f27bf6f,0x3f42beb8,
0xbefc3f58,0xbf5f3f09,0xbe89be60,0x3f77bf7a,0x3ee63cc9,0xbf653f80,0xbf733f31,0x3ea1bf39,0x3f7ebf51,0xbdfb3f13,0xbf4a3f7c,0xbf1d3e2f,
0x3dc9bef1,0x3f7fbf62,0xbdc93ef1,0xbf7f3f62,0xbf223e95,0x3f46bf75,0x3f22be95,0xbf463f75,0xbf7f3f62,0x3dc9bef1,0x3f7fbf62,0xbdc93ef1,
0xbf463f75,0xbf223e95,0x3f46bf75,0x3f22be95,0x3f77bf58,0xbe893f09,0xbefc3e60,0x3f5fbf7a,0x3f73bf80,0x3ea1bcc9,0xbf653f39,0x3ee6bf31,
0x3f1dbf51,0x3f4abf13,0xbf7e3f7c,0xbdfbbe2f,0x3d97beb8,0x3f7fbf6f,0xbf423f6a,0xbf273ecf,0xbedb3f18,0xbf673f4e,0x3f67bf4e,0xbedb3f18,
0xbd493e79,0xbf803f78,0x3f80bf78,0xbd493e79,0x3eacbe16,0xbf713f7d,0x3f71bf7d,0x3eacbe16,0x3f2cbf04,0xbf3e3f5c,0x3f3ebf5c,0x3f2cbf04,
0xbf513f42,0x3f13bf27,0xbf7c3f7f,0xbe2f3d97,0xbf6a3f5f,0x3ecfbefc,0xbf6f3f77,0xbeb83e89,0xbf7a3f73,0x3e60bea1,0xbf583f65,0xbf093ee6,
0xbf803f7e,0x3cc9bdfb,0xbf393f4a,0xbf313f1d,0x3f803f80,0xbf353f35,0x3f803f80,0xbf353f35,0x3f803f80,0xbf353f35,0x3f803f80,0xbf353f35,
0x3f803f80,0xbf353f35,0x3f803f80,0xbf353f35,0x3f803f80,0xbf353f35,0x3f803f80,0xbf353f35,0xbf7cbf7f,0x3e2f3d97,0xbf13bf27,0x3f513f42,
0xbf6fbf77,0x3eb83e89,0xbecfbefc,0x3f6a3f5f,0xbf58bf65,0x3f093ee6,0xbe60bea1,0x3f7a3f73,0xbf39bf4a,0x3f313f1d,0xbcc9bdfb,0x3f803f7e,
0x3f713f7d,0xbeacbe16,0xbeacbe16,0xbf71bf7d,0x3f3e3f5c,0xbf2cbf04,0xbf2cbf04,0xbf3ebf5c,0x3edb3f18,0xbf67bf4e,0xbf67bf4e,0xbedbbf18,
0x3d493e79,0xbf80bf78,0xbf80bf78,0xbd49be79,0xbf5fbf7a,0x3efc3e60,0x3f773f58,0x3e893f09,0xbee6bf31,0x3f653f39,0x3f733f80,0xbea1bcc9,
0x3dfbbe2f,0x3f7e3f7c,0x3f1d3f51,0xbf4abf13,0x3f273ecf,0x3f423f6a,0x3d973eb8,0xbf7fbf6f,0x3f463f75,0xbf22be95,0xbf46bf75,0x3f223e95,
0x3dc93ef1,0xbf7fbf62,0xbdc9bef1,0x3f7f3f62,0xbf22be95,0xbf46bf75,0x3f223e95,0x3f463f75,0xbf7fbf62,0xbdc9bef1,0x3f7f3f62,0x3dc93ef1,
0xbf27bf6f,0x3f423eb8,0xbd973ecf,0xbf7fbf6a,0x3e89be60,0x3f773f7a,0xbf5fbf09,0xbefcbf58,0x3f733f31,0x3ea13f39,0xbf65bf80,0x3ee6bcc9,
0x3f4a3f7c,0xbf1dbe2f,0xbdfbbf13,0x3f7e3f51,0x3f043f67,0xbf5cbedb,0x3f5c3edb,0x3f043f67,0xbf18bd49,0xbf4ebf80,0x3f4e3f80,0xbf18bd49,
0xbf78bf71,0x3e79beac,0xbe793eac,0xbf78bf71,0xbe16bf2c,0x3f7d3f3e,0xbf7dbf3e,0xbe16bf2c,0xbeb8bf5f,0x3f6f3efc,0xbf6abf77,0x3ecfbe89,
0x3f583ea1,0x3f093f73,0x3e60bee6,0x3f7a3f65,0x3f313f7e,0xbf39bdfb,0x3f803f4a,0xbcc93f1d,0xbf133d97,0xbf51bf7f,0x3e2f3f42,0xbf7cbf27,
0x3e483f55,0xbf7bbf0e,0x3e483f55,0xbf7bbf0e,0xbf7bbf0e,0xbe48bf55,0xbf7bbf0e,0xbe48bf55,0xbe48bf55,0x3f7b3f0e,0xbe48bf55,0x3f7b3f0e,
0x3f7b3f0e,0x3e483f55,0x3f7b3f0e,0x3e483f55,0xbcc9bf4a,0x3f803f1d,0x3f31bdfb,0x3f393f7e,0x3f7c3f42,0xbe2f3f27,0x3f133f7f,0xbf51bd97,
0xbeb83efc,0xbf6fbf5f,0xbf6abe89,0xbecfbf77,0xbf58bf73,0x3f09bea1,0xbe60bf65,0x3f7a3ee6,0xbe163f3e,0xbf7dbf2c,0xbf7dbf2c,0x3e16bf3e,
0xbf5cbf67,0x3f04bedb,0x3f04bedb,0x3f5c3f67,0x3f4ebd49,0x3f183f80,0x3f183f80,0xbf4e3d49,0x3e793f71,0xbf78beac,0xbf78beac,0xbe79bf71,
0x3ea1bf31,0x3f733f39,0x3ee63f80,0xbf65bcc9,0x3f1d3f7c,0xbf4a3e2f,0xbf7ebf13,0x3dfbbf51,0xbf7fbecf,0xbd97bf6a,0x3f27beb8,0x3f423f6f,
0x3efcbf09,0x3f5f3f58,0x3e893f7a,0xbf77be60,0xbef13f22,0xbf62bf46,0x3ef1bf22,0x3f623f46,0xbe95bf7f,0x3f753dc9,0x3e953f7f,0xbf75bdc9,
0x3f623f46,0xbef13f22,0xbf62bf46,0x3ef1bf22,0xbf75bdc9,0xbe95bf7f,0x3f753dc9,0x3e953f7f,0x3f1dbf13,0x3f4a3f51,0xbf7ebe2f,0xbdfbbf7c,
0xbd973f6f,0xbf7fbeb8,0x3f42becf,0x3f273f6a,0xbefcbf7a,0x3f5fbe60,0xbe893f58,0xbf77bf09,0x3f653f31,0xbee63f39,0xbea1bf80,0x3f73bcc9,
0xbf3e3f04,0xbf2cbf5c,0x3f2c3f5c,0xbf3e3f04,0x3edbbf4e,0x3f673f18,0xbf67bf18,0x3edbbf4e,0xbd493f78,0xbf80be79,0x3f803e79,0xbd493f78,
0xbeacbf7d,0x3f71be16,0xbf713e16,0xbeacbf7d,0x3f58bee6,0x3f093f65,0x3e60bf73,0x3f7a3ea1,0xbf393f1d,0xbf31bf4a,0xbcc93f7e,0xbf80bdfb,
0x3f13bf42,0x3f513f27,0xbe2fbf7f,0x3f7cbd97,0xbecf3f5f,0xbf6abefc,0x3eb83f77,0xbf6f3e89,0xbf6d3ec4,0xbec4bf6d,0xbf6d3ec4,0xbec4bf6d,
0x3f6dbec4,0x3ec43f6d,0x3f6dbec4,0x3ec43f6d,0xbf6d3ec4,0xbec4bf6d,0xbf6d3ec4,0xbec4bf6d,0x3f6dbec4,0x3ec43f6d,0x3f6dbec4,0x3ec43f6d,
0x3f7abea1,0x3e603f73,0x3f583ee6,0xbf093f65,0xbf803dfb,0xbcc9bf7e,0xbf39bf1d,0x3f31bf4a,0x3f7c3d97,0xbe2f3f7f,0x3f133f42,0xbf513f27,
0xbf6fbe89,0x3eb8bf77,0xbecfbf5f,0x3f6abefc,0xbf803e79,0xbd49bf78,0xbd49bf78,0x3f80be79,0x3f713e16,0xbeac3f7d,0xbeac3f7d,0xbf71be16,
0xbf3ebf04,0x3f2cbf5c,0x3f2cbf5c,0x3f3e3f04,0x3edb3f4e,0xbf673f18,0xbf673f18,0xbedbbf4e,0x3f7ebe2f,0xbdfb3f7c,0xbf4a3f51,0xbf1dbf13,
0xbf42becf,0x3f27bf6a,0x3f7fbeb8,0x3d973f6f,0x3e893f58,0xbf773f09,0xbf5fbe60,0x3efcbf7a,0x3ea1bf80,0x3f733cc9,0x3ee63f39,0xbf653f31,
0xbf753dc9,0x3e95bf7f,0x3f75bdc9,0xbe953f7f,0x3ef13f22,0xbf623f46,0xbef1bf22,0x3f62bf46,0x3e95bf7f,0x3f75bdc9,0xbe953f7f,0xbf753dc9,
0xbf623f46,0xbef1bf22,0x3f62bf46,0x3ef13f22,0x3f65bcc9,0xbee63f80,0xbea1bf31,0x3f73bf39,0xbdfbbf51,0x3f7ebf13,0xbf1d3f7c,0xbf4abe2f,
0xbf423f6f,0xbf27beb8,0x3f7fbecf,0xbd973f6a,0x3f77be60,0xbe893f7a,0xbefcbf09,0x3f5fbf58,0xbf4ebd49,0x3f18bf80,0xbf183f80,0xbf4ebd49,
0xbe793f71,0xbf783eac,0x3f78beac,0xbe793f71,0x3f7dbf2c,0x3e163f3e,0xbe16bf3e,0x3f7dbf2c,0xbf04bedb,0x3f5cbf67,0xbf5c3f67,0xbf04bedb,
0x3f313dfb,0xbf393f7e,0x3f80bf1d,0xbcc93f4a,0x3f13bf7f,0x3f51bd97,0xbe2fbf27,0x3f7cbf42,0xbf6a3e89,0x3ecfbf77,0xbf6f3f5f,0xbeb8befc,
0xbe603f65,0xbf7a3ee6,0x3f093ea1,0xbf583f73,0xbf0ebe48,0x3f55bf7b,0xbf0ebe48,0x3f55bf7b,0xbf553f7b,0xbf0ebe48,0xbf553f7b,0xbf0ebe48,
0x3f0e3e48,0xbf553f7b,0x3f0e3e48,0xbf553f7b,0x3f55bf7b,0x3f0e3e48,0x3f55bf7b,0x3f0e3e48,0x3ecf3e89,0xbf6a3f77,0xbeb83f5f,0xbf6f3efc,
0x3f7abf65,0x3e603ee6,0x3f58bea1,0xbf093f73,0xbcc9bf1d,0x3f80bf4a,0x3f31bf7e,0x3f39bdfb,0xbf7c3f27,0x3e2fbf42,0xbf13bd97,0x3f51bf7f,
0xbe79beac,0x3f78bf71,0x3f78bf71,0x3e793eac,0xbf7d3f3e,0x3e16bf2c,0x3e16bf2c,0x3f7dbf3e,0xbf043f67,0xbf5c3edb,0xbf5c3edb,0x3f04bf67,
0x3f18bd49,0xbf4e3f80,0xbf4e3f80,0xbf183d49,0x3d973ecf,0xbf7f3f6a,0xbf423eb8,0x3f27bf6f,0x3f5fbf09,0xbefc3f58,0xbf773f7a,0xbe89be60,
0x3f65bf80,0x3ee63cc9,0xbea13f39,0xbf733f31,0x3dfbbf13,0x3f7ebf51,0x3f1dbe2f,0xbf4a3f7c,0x3dc9bef1,0x3f7fbf62,0xbdc93ef1,0xbf7f3f62,
0xbf223e95,0x3f46bf75,0x3f22be95,0xbf463f75,0xbf7f3f62,0x3dc9bef1,0x3f7fbf62,0xbdc93ef1,0xbf463f75,0xbf223e95,0x3f46bf75,0x3f22be95,
0xbe893f09,0xbf773f58,0x3f5fbf7a,0x3efcbe60,0x3ea1bcc9,0xbf733f80,0x3ee6bf31,0x3f65bf39,0x3f4abf13,0xbf1d3f51,0xbdfbbe2f,0x3f7ebf7c,
0x3f7fbf6f,0xbd973eb8,0xbf273ecf,0x3f42bf6a,0x3edbbf18,0x3f67bf4e,0xbf673f4e,0x3edbbf18,0x3d49be79,0x3f80bf78,0xbf803f78,0x3d49be79,
0xbeac3e16,0x3f71bf7d,0xbf713f7d,0xbeac3e16,0xbf2c3f04,0x3f3ebf5c,0xbf3e3f5c,0xbf2c3f04,0xbf133f27,0xbf513f42,0x3e2fbd97,0xbf7c3f7f,
0xbecf3efc,0xbf6a3f5f,0x3eb8be89,0xbf6f3f77,0xbe603ea1,0xbf7a3f73,0x3f09bee6,0xbf583f65,0xbcc93dfb,0xbf803f7e,0x3f31bf1d,0xbf393f4a,
0x3f803f80,0xbf353f35,0x3f803f80,0xbf353f35,0x3f803f80,0xbf353f35,0x3f803f80,0xbf353f35,0x3f803f80,0xbf353f35,0x3f803f80,0xbf353f35,
0x3f803f80,0xbf353f35,0x3f803f80,0xbf353f35,0x3e2f3d97,0x3f7c3f7f,0x3f513f42,0x3f133f27,0x3eb83e89,0x3f6f3f77,0x3f6a3f5f,0x3ecf3efc,
0x3f093ee6,0x3f583f65,0x3f7a3f73,0x3e603ea1,0x3f313f1d,0x3f393f4a,0x3f803f7e,0x3cc93dfb,0xbf71bf7d,0x3eac3e16,0x3eac3e16,0x3f713f7d,
0xbf3ebf5c,0x3f2c3f04,0x3f2c3f04,0x3f3e3f5c,0xbedbbf18,0x3f673f4e,0x3f673f4e,0x3edb3f18,0xbd49be79,0x3f803f78,0x3f803f78,0x3d493e79,
0xbefcbe60,0xbf5fbf7a,0xbe89bf09,0x3f773f58,0xbf65bf39,0xbee6bf31,0x3ea13cc9,0x3f733f80,0xbf7ebf7c,0x3dfbbe2f,0x3f4a3f13,0x3f1d3f51,
0xbf42bf6a,0x3f273ecf,0x3f7f3f6f,0x3d973eb8,0x3f463f75,0xbf22be95,0xbf46bf75,0x3f223e95,0x3dc93ef1,0xbf7fbf62,0xbdc9bef1,0x3f7f3f62,
0xbf22be95,0xbf46bf75,0x3f223e95,0x3f463f75,0xbf7fbf62,0xbdc9bef1,0x3f7f3f62,0x3dc93ef1,0x3f423eb8,0x3f273f6f,0xbf7fbf6a,0x3d97becf,
0x3f773f7a,0xbe893e60,0xbefcbf58,0x3f5f3f09,0x3ea13f39,0xbf73bf31,0x3ee6bcc9,0x3f653f80,0xbf1dbe2f,0xbf4abf7c,0x3f7e3f51,0x3dfb3f13,
0xbf04bf67,0x3f5c3edb,0xbf5cbedb,0xbf04bf67,0x3f183d49,0x3f4e3f80,0xbf4ebf80,0x3f183d49,0x3f783f71,0xbe793eac,0x3e79beac,0x3f783f71,
0x3e163f2c,0xbf7dbf3e,0x3f7d3f3e,0x3e163f2c,0xbf6fbefc,0xbeb8bf5f,0xbecf3e89,0xbf6abf77,0xbf09bf73,0x3f583ea1,0xbf7abf65,0x3e60bee6,
0x3f393dfb,0x3f313f7e,0x3cc9bf1d,0x3f803f4a,0x3f513f7f,0xbf133d97,0x3f7c3f27,0x3e2f3f42,0x3e483f55,0xbf7bbf0e,0x3e483f55,0xbf7bbf0e,
0xbf7bbf0e,0xbe48bf55,0xbf7bbf0e,0xbe48bf55,0xbe48bf55,0x3f7b3f0e,0xbe48bf55,0x3f7b3f0e,0x3f7b3f0e,0x3e483f55,0x3f7b3f0e,0x3e483f55,
0x3f803f1d,0x3cc93f4a,0x3f393f7e,0xbf313dfb,0xbe2f3f27,0xbf7cbf42,0xbf51bd97,0xbf13bf7f,0xbf6fbf5f,0x3eb8befc,0xbecfbf77,0x3f6a3e89,
0x3f09bea1,0x3f583f73,0x3f7a3ee6,0x3e603f65,0x3e16bf3e,0x3f7d3f2c,0x3f7d3f2c,0xbe163f3e,0x3f5c3f67,0xbf043edb,0xbf043edb,0xbf5cbf67,
0xbf4e3d49,0xbf18bf80,0xbf18bf80,0x3f4ebd49,0xbe79bf71,0x3f783eac,0x3f783eac,0x3e793f71,0xbf73bf39,0x3ea1bf31,0x3f653cc9,0x3ee63f80,
0x3f4abe2f,0x3f1d3f7c,0xbdfb3f51,0xbf7ebf13,0x3d973f6a,0xbf7fbecf,0xbf42bf6f,0x3f27beb8,0xbf5fbf58,0x3efcbf09,0x3f773e60,0x3e893f7a,
0xbef13f22,0xbf62bf46,0x3ef1bf22,0x3f623f46,0xbe95bf7f,0x3f753dc9,0x3e953f7f,0xbf75bdc9,0x3f623f46,0xbef13f22,0xbf62bf46,0x3ef1bf22,
0xbf75bdc9,0xbe95bf7f,0x3f753dc9,0x3e953f7f,0x3f4a3f51,0xbf1d3f13,0xbdfbbf7c,0x3f7e3e2f,0xbf7fbeb8,0x3d97bf6f,0x3f273f6a,0xbf423ecf,
0x3f5fbe60,0x3efc3f7a,0xbf77bf09,0x3e89bf58,0xbee63f39,0xbf65bf31,0x3f73bcc9,0x3ea13f80,0x3f3ebf04,0x3f2c3f5c,0xbf2cbf5c,0x3f3ebf04,
0xbedb3f4e,0xbf67bf18,0x3f673f18,0xbedb3f4e,0x3d49bf78,0x3f803e79,0xbf80be79,0x3d49bf78,0x3eac3f7d,0xbf713e16,0x3f71be16,0x3eac3f7d,
0xbf09bf65,0x3f58bee6,0xbf7abea1,0x3e60bf73,0x3f313f4a,0xbf393f1d,0x3f803dfb,0xbcc93f7e,0xbf51bf27,0x3f13bf42,0xbf7c3d97,0xbe2fbf7f,
0x3f6a3efc,0xbecf3f5f,0x3f6fbe89,0x3eb83f77,0xbf6d3ec4,0xbec4bf6d,0xbf6d3ec4,0xbec4bf6d,0x3f6dbec4,0x3ec43f6d,0x3f6dbec4,0x3ec43f6d,
0xbf6d3ec4,0xbec4bf6d,0xbf6d3ec4,0xbec4bf6d,0x3f6dbec4,0x3ec43f6d,0x3f6dbec4,0x3ec43f6d,0x3e603f73,0xbf7a3ea1,0xbf093f65,0xbf58bee6,
0xbcc9bf7e,0x3f80bdfb,0x3f31bf4a,0x3f393f1d,0xbe2f3f7f,0xbf7cbd97,0xbf513f27,0xbf13bf42,0x3eb8bf77,0x3f6f3e89,0x3f6abefc,0x3ecf3f5f,
0x3f80be79,0x3d493f78,0x3d493f78,0xbf803e79,0xbf71be16,0x3eacbf7d,0x3eacbf7d,0x3f713e16,0x3f3e3f04,0xbf2c3f5c,0xbf2c3f5c,0xbf3ebf04,
0xbedbbf4e,0x3f67bf18,0x3f67bf18,0x3edb3f4e,0x3dfbbf7c,0x3f7ebe2f,0x3f1d3f13,0xbf4a3f51,0xbf273f6a,0xbf42becf,0xbd97bf6f,0x3f7fbeb8,
0x3f77bf09,0x3e893f58,0xbefc3f7a,0xbf5fbe60,0xbf73bcc9,0x3ea1bf80,0x3f65bf31,0x3ee63f39,0xbf753dc9,0x3e95bf7f,0x3f75bdc9,0xbe953f7f,
0x3ef13f22,0xbf623f46,0xbef1bf22,0x3f62bf46,0x3e95bf7f,0x3f75bdc9,0xbe953f7f,0xbf753dc9,0xbf623f46,0xbef1bf22,0x3f62bf46,0x3ef13f22,
0xbee63f80,0xbf653cc9,0x3f73bf39,0x3ea13f31,0x3f7ebf13,0x3dfb3f51,0xbf4abe2f,0x3f1dbf7c,0xbf27beb8,0x3f42bf6f,0xbd973f6a,0xbf7f3ecf,
0xbe893f7a,0xbf773e60,0x3f5fbf58,0x3efc3f09,0x3f4e3d49,0xbf183f80,0x3f18bf80,0x3f4e3d49,0x3e79bf71,0x3f78beac,0xbf783eac,0x3e79bf71,
0xbf7d3f2c,0xbe16bf3e,0x3e163f3e,0xbf7d3f2c,0x3f043edb,0xbf5c3f67,0x3f5cbf67,0x3f043edb,0x3f39bf7e,0x3f313dfb,0x3cc9bf4a,0x3f80bf1d,
0xbf513d97,0x3f13bf7f,0xbf7c3f42,0xbe2fbf27,0xbecf3f77,0xbf6a3e89,0x3eb83efc,0xbf6f3f5f,0x3f7abee6,0xbe603f65,0x3f58bf73,0x3f093ea1,
0xbf0ebe48,0x3f55bf7b,0xbf0ebe48,0x3f55bf7b,0xbf553f7b,0xbf0ebe48,0xbf553f7b,0xbf0ebe48,0x3f0e3e48,0xbf553f7b,0x3f0e3e48,0xbf553f7b,
0x3f55bf7b,0x3f0e3e48,0x3f55bf7b,0x3f0e3e48,0xbf6a3f77,0xbecfbe89,0xbf6f3efc,0x3eb8bf5f,0x3e603ee6,0xbf7a3f65,0xbf093f73,0xbf583ea1,
0x3f80bf4a,0x3cc93f1d,0x3f39bdfb,0xbf313f7e,0x3e2fbf42,0x3f7cbf27,0x3f51bf7f,0x3f133d97,0x3e793eac,0xbf783f71,0xbf783f71,0xbe79beac,
0x3f7dbf3e,0xbe163f2c,0xbe163f2c,0xbf7d3f3e,0x3f04bf67,0x3f5cbedb,0x3f5cbedb,0xbf043f67,0xbf183d49,0x3f4ebf80,0x3f4ebf80,0x3f18bd49,
0x3f7fbf6a,0x3d973ecf,0xbf273f6f,0xbf423eb8,0x3efcbf58,0x3f5fbf09,0x3e893e60,0xbf773f7a,0xbee6bcc9,0x3f65bf80,0x3f73bf31,0xbea13f39,
0xbf7e3f51,0x3dfbbf13,0x3f4abf7c,0x3f1dbe2f,0x3dc9bef1,0x3f7fbf62,0xbdc93ef1,0xbf7f3f62,0xbf223e95,0x3f46bf75,0x3f22be95,0xbf463f75,
0xbf7f3f62,0x3dc9bef1,0x3f7fbf62,0xbdc93ef1,0xbf463f75,0xbf223e95,0x3f46bf75,0x3f22be95,0xbf773f58,0x3e89bf09,0x3efcbe60,0xbf5f3f7a,
0xbf733f80,0xbea13cc9,0x3f65bf39,0xbee63f31,0xbf1d3f51,0xbf4a3f13,0x3f7ebf7c,0x3dfb3e2f,0xbd973eb8,0xbf7f3f6f,0x3f42bf6a,0x3f27becf,
0xbedb3f18,0xbf673f4e,0x3f67bf4e,0xbedb3f18,0xbd493e79,0xbf803f78,0x3f80bf78,0xbd493e79,0x3eacbe16,0xbf713f7d,0x3f71bf7d,0x3eacbe16,
0x3f2cbf04,0xbf3e3f5c,0x3f3ebf5c,0x3f2cbf04,0x3f51bf42,0xbf133f27,0x3f7cbf7f,0x3e2fbd97,0x3f6abf5f,0xbecf3efc,0x3f6fbf77,0x3eb8be89,
0x3f7abf73,0xbe603ea1,0x3f58bf65,0x3f09bee6,0x3f80bf7e,0xbcc93dfb,0x3f39bf4a,0x3f31bf1d,0x3f803f80,0x3f803f80,0x3f803f80,0x3f803f80,
0x0,0x0,0x0,0x0,0x3f803f80,0x3f803f80,0x3f803f80,0x3f803f80,0x0,0x0,0x0,0x0,
0x3f803f80,0x3f803f80,0x3f803f80,0x3f803f80,0x0,0x0,0x0,0x0,0x3f803f80,0x3f803f80,0x3f803f80,0x3f803f80,
0x0,0x0,0x0,0x0,0x3e480000,0x3f0e3ec4,0x3f553f35,0x3f7b3f6d,0x3f7b3f80,0x3f553f6d,0x3f0e3f35,0x3e483ec4,
0x3f7b3f80,0x3f553f6d,0x3f0e3f35,0x3e483ec4,0xbe480000,0xbf0ebec4,0xbf55bf35,0xbf7bbf6d,0xbe480000,0xbf0ebec4,0xbf55bf35,0xbf7bbf6d,
0xbf7bbf80,0xbf55bf6d,0xbf0ebf35,0xbe48bec4,0xbf7bbf80,0xbf55bf6d,0xbf0ebf35,0xbe48bec4,0x3e480000,0x3f0e3ec4,0x3f553f35,0x3f7b3f6d,
0xbf6dbf80,0xbec4bf35,0x3ec40000,0x3f6d3f35,0xbec40000,0xbf6dbf35,0xbf6dbf80,0xbec4bf35,0x3f6d3f80,0x3ec43f35,0xbec40000,0xbf6dbf35,
0x3ec40000,0x3f6d3f35,0x3f6d3f80,0x3ec43f35,0xbf6dbf80,0xbec4bf35,0x3ec40000,0x3f6d3f35,0xbec40000,0xbf6dbf35,0xbf6dbf80,0xbec4bf35,
0x3f6d3f80,0x3ec43f35,0xbec40000,0xbf6dbf35,0x3ec40000,0x3f6d3f35,0x3f6d3f80,0x3ec43f35,0xbf55bf80,0x3e48bec4,0x3f7b3f35,0x3f0e3f6d,
0x3f0e0000,0x3f7b3f6d,0x3e483f35,0xbf55bec4,0x3f0e0000,0x3f7b3f6d,0x3e483f35,0xbf55bec4,0x3f553f80,0xbe483ec4,0xbf7bbf35,0xbf0ebf6d,
0x3f553f80,0xbe483ec4,0xbf7bbf35,0xbf0ebf6d,0xbf0e0000,0xbf7bbf6d,0xbe48bf35,0x3f553ec4,0xbf0e0000,0xbf7bbf6d,0xbe48bf35,0x3f553ec4,
0xbf55bf80,0x3e48bec4,0x3f7b3f35,0x3f0e3f6d,0x3f353f80,0xbf350000,0xbf35bf80,0x3f350000,0x3f350000,0x3f353f80,0xbf350000,0xbf35bf80,
0x3f353f80,0xbf350000,0xbf35bf80,0x3f350000,0x3f350000,0x3f353f80,0xbf350000,0xbf35bf80,0x3f353f80,0xbf350000,0xbf35bf80,0x3f350000,
0x3f350000,0x3f353f80,0xbf350000,0xbf35bf80,0x3f353f80,0xbf350000,0xbf35bf80,0x3f350000,0x3f350000,0x3f353f80,0xbf350000,0xbf35bf80,
0xbf550000,0xbe48bf6d,0x3f7b3f35,0xbf0e3ec4,0xbf0ebf80,0x3f7b3ec4,0xbe483f35,0xbf55bf6d,0xbf0ebf80,0x3f7b3ec4,0xbe483f35,0xbf55bf6d,
0x3f550000,0x3e483f6d,0xbf7bbf35,0x3f0ebec4,0x3f550000,0x3e483f6d,0xbf7bbf35,0x3f0ebec4,0x3f0e3f80,0xbf7bbec4,0x3e48bf35,0x3f553f6d,
0x3f0e3f80,0xbf7bbec4,0x3e48bf35,0x3f553f6d,0xbf550000,0xbe48bf6d,0x3f7b3f35,0xbf0e3ec4,0xbec4bf80,0x3f6d3f35,0xbf6d0000,0x3ec4bf35,
0xbf6d0000,0x3ec4bf35,0x3ec43f80,0xbf6dbf35,0x3ec43f80,0xbf6dbf35,0x3f6d0000,0xbec43f35,0x3f6d0000,0xbec43f35,0xbec4bf80,0x3f6d3f35,
0xbec4bf80,0x3f6d3f35,0xbf6d0000,0x3ec4bf35,0xbf6d0000,0x3ec4bf35,0x3ec43f80,0xbf6dbf35,0x3ec43f80,0xbf6dbf35,0x3f6d0000,0xbec43f35,
0x3f6d0000,0xbec43f35,0xbec4bf80,0x3f6d3f35,0x3e483f80,0xbf0ebf6d,0x3f553f35,0xbf7bbec4,0xbf7b0000,0x3f55bec4,0xbf0e3f35,0x3e48bf6d,
0xbf7b0000,0x3f55bec4,0xbf0e3f35,0x3e48bf6d,0xbe48bf80,0x3f0e3f6d,0xbf55bf35,0x3f7b3ec4,0xbe48bf80,0x3f0e3f6d,0xbf55bf35,0x3f7b3ec4,
0x3f7b0000,0xbf553ec4,0x3f0ebf35,0xbe483f6d,0x3f7b0000,0xbf553ec4,0x3f0ebf35,0xbe483f6d,0x3e483f80,0xbf0ebf6d,0x3f553f35,0xbf7bbec4,
0x80008000,0x80008000,0x80008000,0x80008000,0x3f803f80,0x3f803f80,0x3f803f80,0x3f803f80,0x80008000,0x80008000,0x80008000,0x80008000,
0x3f803f80,0x3f803f80,0x3f803f80,0x3f803f80,0x80008000,0x80008000,0x80008000,0x80008000,0x3f803f80,0x3f803f80,0x3f803f80,0x3f803f80,
0x80008000,0x80008000,0x80008000,0x80008000,0x3f803f80,0x3f803f80,0x3f803f80,0x3f803f80,0x3f7b3f80,0x3f553f6d,0x3f0e3f35,0x3e483ec4,
0xbe488000,0xbf0ebec4,0xbf55bf35,0xbf7bbf6d,0xbe480000,0xbf0ebec4,0xbf55bf35,0xbf7bbf6d,0xbf7bbf80,0xbf55bf6d,0xbf0ebf35,0xbe48bec4,
0xbf7bbf80,0xbf55bf6d,0xbf0ebf35,0xbe48bec4,0x3e488000,0x3f0e3ec4,0x3f553f35,0x3f7b3f6d,0x3e480000,0x3f0e3ec4,0x3f553f35,0x3f7b3f6d,
0x3f7b3f80,0x3f553f6d,0x3f0e3f35,0x3e483ec4,0x3ec48000,0x3f6d3f35,0x3f6d3f80,0x3ec43f35,0xbf6dbf80,0xbec4bf35,0x3ec40000,0x3f6d3f35,
0xbec48000,0xbf6dbf35,0xbf6dbf80,0xbec4bf35,0x3f6d3f80,0x3ec43f35,0xbec40000,0xbf6dbf35,0x3ec48000,0x3f6d3f35,0x3f6d3f80,0x3ec43f35,
0xbf6dbf80,0xbec4bf35,0x3ec40000,0x3f6d3f35,0xbec48000,0xbf6dbf35,0xbf6dbf80,0xbec4bf35,0x3f6d3f80,0x3ec43f35,0xbec40000,0xbf6dbf35,
0x3f0e0000,0x3f7b3f6d,0x3e483f35,0xbf55bec4,0x3f553f80,0xbe483ec4,0xbf7bbf35,0xbf0ebf6d,0x3f553f80,0xbe483ec4,0xbf7bbf35,0xbf0ebf6d,
0xbf0e8000,0xbf7bbf6d,0xbe48bf35,0x3f553ec4,0xbf0e0000,0xbf7bbf6d,0xbe48bf35,0x3f553ec4,0xbf55bf80,0x3e48bec4,0x3f7b3f35,0x3f0e3f6d,
0xbf55bf80,0x3e48bec4,0x3f7b3f35,0x3f0e3f6d,0x3f0e8000,0x3f7b3f6d,0x3e483f35,0xbf55bec4,0xbf358000,0xbf35bf80,0x3f358000,0x3f353f80,
0x3f353f80,0xbf350000,0xbf35bf80,0x3f350000,0xbf358000,0xbf35bf80,0x3f358000,0x3f353f80,0x3f353f80,0xbf350000,0xbf35bf80,0x3f350000,
0xbf358000,0xbf35bf80,0x3f358000,0x3f353f80,0x3f353f80,0xbf350000,0xbf35bf80,0x3f350000,0xbf358000,0xbf35bf80,0x3f358000,0x3f353f80,
0x3f353f80,0xbf350000,0xbf35bf80,0x3f350000,0xbf0ebf80,0x3f7b3ec4,0xbe483f35,0xbf55bf6d,0x3f558000,0x3e483f6d,0xbf7bbf35,0x3f0ebec4,
0x3f550000,0x3e483f6d,0xbf7bbf35,0x3f0ebec4,0x3f0e3f80,0xbf7bbec4,0x3e48bf35,0x3f553f6d,0x3f0e3f80,0xbf7bbec4,0x3e48bf35,0x3f553f6d,
0xbf558000,0xbe48bf6d,0x3f7b3f35,0xbf0e3ec4,0xbf550000,0xbe48bf6d,0x3f7b3f35,0xbf0e3ec4,0xbf0ebf80,0x3f7b3ec4,0xbe483f35,0xbf55bf6d,
0x3f6d8000,0xbec43f35,0xbec4bf80,0x3f6d3f35,0xbec4bf80,0x3f6d3f35,0xbf6d0000,0x3ec4bf35,0xbf6d8000,0x3ec4bf35,0x3ec43f80,0xbf6dbf35,
0x3ec43f80,0xbf6dbf35,0x3f6d0000,0xbec43f35,0x3f6d8000,0xbec43f35,0xbec4bf80,0x3f6d3f35,0xbec4bf80,0x3f6d3f35,0xbf6d0000,0x3ec4bf35,
0xbf6d8000,0x3ec4bf35,0x3ec43f80,0xbf6dbf35,0x3ec43f80,0xbf6dbf35,0x3f6d0000,0xbec43f35,0xbf7b0000,0x3f55bec4,0xbf0e3f35,0x3e48bf6d,
0xbe48bf80,0x3f0e3f6d,0xbf55bf35,0x3f7b3ec4,0xbe48bf80,0x3f0e3f6d,0xbf55bf35,0x3f7b3ec4,0x3f7b8000,0xbf553ec4,0x3f0ebf35,0xbe483f6d,
0x3f7b0000,0xbf553ec4,0x3f0ebf35,0xbe483f6d,0x3e483f80,0xbf0ebf6d,0x3f553f35,0xbf7bbec4,0x3e483f80,0xbf0ebf6d,0x3f553f35,0xbf7bbec4,
0xbf7b8000,0x3f55bec4,0xbf0e3f35,0x3e48bf6d,0x3f80,0xbf80,0x3f80,0xbf80,0x3f800000,0xbf800000,0x3f800000,0xbf800000,
0x3f80,0xbf80,0x3f80,0xbf80,0x3f800000,0xbf800000,0x3f800000,0xbf800000,0x3f80,0xbf80,0x3f80,0xbf80,
0x3f800000,0xbf800000,0x3f800000,0xbf800000,0x3f80,0xbf80,0x3f80,0xbf80,0x3f800000,0xbf800000,0x3f800000,0xbf800000,
0x3f7b0000,0xbf55bec4,0x3f0e3f35,0xbe48bf6d,0xbe483f80,0x3f0ebf6d,0xbf553f35,0x3f7bbec4,0xbe483f80,0x3f0ebf6d,0xbf553f35,0x3f7bbec4,
0xbf7b0000,0x3f553ec4,0xbf0ebf35,0x3e483f6d,0xbf7b0000,0x3f553ec4,0xbf0ebf35,0x3e483f6d,0x3e48bf80,0xbf0e3f6d,0x3f55bf35,0xbf7b3ec4,
0x3e48bf80,0xbf0e3f6d,0x3f55bf35,0xbf7b3ec4,0x3f7b0000,0xbf55bec4,0x3f0e3f35,0xbe48bf6d,0x3ec4bf80,0xbf6d3f35,0x3f6d0000,0xbec4bf35,
0xbf6d0000,0x3ec43f35,0x3ec4bf80,0xbf6d3f35,0xbec43f80,0x3f6dbf35,0xbf6d0000,0x3ec43f35,0x3f6d0000,0xbec4bf35,0xbec43f80,0x3f6dbf35,
0x3ec4bf80,0xbf6d3f35,0x3f6d0000,0xbec4bf35,0xbf6d0000,0x3ec43f35,0x3ec4bf80,0xbf6d3f35,0xbec43f80,0x3f6dbf35,0xbf6d0000,0x3ec43f35,
0x3f6d0000,0xbec4bf35,0xbec43f80,0x3f6dbf35,0x3f0ebf80,0xbf7b3ec4,0x3e483f35,0x3f55bf6d,0x3f550000,0x3e48bf6d,0xbf7b3f35,0x3f0e3ec4,
0x3f550000,0x3e48bf6d,0xbf7b3f35,0x3f0e3ec4,0xbf0e3f80,0x3f7bbec4,0xbe48bf35,0xbf553f6d,0xbf0e3f80,0x3f7bbec4,0xbe48bf35,0xbf553f6d,
0xbf550000,0xbe483f6d,0x3f7bbf35,0xbf0ebec4,0xbf550000,0xbe483f6d,0x3f7bbf35,0xbf0ebec4,0x3f0ebf80,0xbf7b3ec4,0x3e483f35,0x3f55bf6d,
0xbf353f80,0x3f350000,0x3f35bf80,0xbf350000,0x3f350000,0x3f35bf80,0xbf350000,0xbf353f80,0xbf353f80,0x3f350000,0x3f35bf80,0xbf350000,
0x3f350000,0x3f35bf80,0xbf350000,0xbf353f80,0xbf353f80,0x3f350000,0x3f35bf80,0xbf350000,0x3f350000,0x3f35bf80,0xbf350000,0xbf353f80,
0xbf353f80,0x3f350000,0x3f35bf80,0xbf350000,0x3f350000,0x3f35bf80,0xbf350000,0xbf353f80,0xbf0e0000,0xbf7b3f6d,0xbe483f35,0x3f55bec4,
0x3f55bf80,0xbe48bec4,0xbf7b3f35,0xbf0e3f6d,0x3f55bf80,0xbe48bec4,0xbf7b3f35,0xbf0e3f6d,0x3f0e0000,0x3f7bbf6d,0x3e48bf35,0xbf553ec4,
0x3f0e0000,0x3f7bbf6d,0x3e48bf35,0xbf553ec4,0xbf553f80,0x3e483ec4,0x3f7bbf35,0x3f0ebf6d,0xbf553f80,0x3e483ec4,0x3f7bbf35,0x3f0ebf6d,
0xbf0e0000,0xbf7b3f6d,0xbe483f35,0x3f55bec4,0x3f6dbf80,0x3ec4bf35,0xbec40000,0xbf6d3f35,0xbec40000,0xbf6d3f35,0xbf6d3f80,0xbec43f35,
0xbf6d3f80,0xbec43f35,0x3ec40000,0x3f6dbf35,0x3ec40000,0x3f6dbf35,0x3f6dbf80,0x3ec4bf35,0x3f6dbf80,0x3ec4bf35,0xbec40000,0xbf6d3f35,
0xbec40000,0xbf6d3f35,0xbf6d3f80,0xbec43f35,0xbf6d3f80,0xbec43f35,0x3ec40000,0x3f6dbf35,0x3ec40000,0x3f6dbf35,0x3f6dbf80,0x3ec4bf35,
0xbf7b3f80,0xbf553f6d,0xbf0e3f35,0xbe483ec4,0xbe480000,0xbf0e3ec4,0xbf553f35,0xbf7b3f6d,0xbe480000,0xbf0e3ec4,0xbf553f35,0xbf7b3f6d,
0x3f7bbf80,0x3f55bf6d,0x3f0ebf35,0x3e48bec4,0x3f7bbf80,0x3f55bf6d,0x3f0ebf35,0x3e48bec4,0x3e480000,0x3f0ebec4,0x3f55bf35,0x3f7bbf6d,
0x3e480000,0x3f0ebec4,0x3f55bf35,0x3f7bbf6d,0xbf7b3f80,0xbf553f6d,0xbf0e3f35,0xbe483ec4,0xbf808000,0x3f808000,0xbf808000,0x3f808000,
0x3f80,0xbf80,0x3f80,0xbf80,0xbf808000,0x3f808000,0xbf808000,0x3f808000,0x3f80,0xbf80,0x3f80,0xbf80,
0xbf808000,0x3f808000,0xbf808000,0x3f808000,0x3f80,0xbf80,0x3f80,0xbf80,0xbf808000,0x3f808000,0xbf808000,0x3f808000,
0x3f80,0xbf80,0x3f80,0xbf80,0xbe483f80,0x3f0ebf6d,0xbf553f35,0x3f7bbec4,0xbf7b8000,0x3f553ec4,0xbf0ebf35,0x3e483f6d,
0xbf7b0000,0x3f553ec4,0xbf0ebf35,0x3e483f6d,0x3e48bf80,0xbf0e3f6d,0x3f55bf35,0xbf7b3ec4,0x3e48bf80,0xbf0e3f6d,0x3f55bf35,0xbf7b3ec4,
0x3f7b8000,0xbf55bec4,0x3f0e3f35,0xbe48bf6d,0x3f7b0000,0xbf55bec4,0x3f0e3f35,0xbe48bf6d,0xbe483f80,0x3f0ebf6d,0xbf553f35,0x3f7bbec4,
0x3f6d8000,0xbec4bf35,0xbec43f80,0x3f6dbf35,0x3ec4bf80,0xbf6d3f35,0x3f6d0000,0xbec4bf35,0xbf6d8000,0x3ec43f35,0x3ec4bf80,0xbf6d3f35,
0xbec43f80,0x3f6dbf35,0xbf6d0000,0x3ec43f35,0x3f6d8000,0xbec4bf35,0xbec43f80,0x3f6dbf35,0x3ec4bf80,0xbf6d3f35,0x3f6d0000,0xbec4bf35,
0xbf6d8000,0x3ec43f35,0x3ec4bf80,0xbf6d3f35,0xbec43f80,0x3f6dbf35,0xbf6d0000,0x3ec43f35,0x3f550000,0x3e48bf6d,0xbf7b3f35,0x3f0e3ec4,
0xbf0e3f80,0x3f7bbec4,0xbe48bf35,0xbf553f6d,0xbf0e3f80,0x3f7bbec4,0xbe48bf35,0xbf553f6d,0xbf558000,0xbe483f6d,0x3f7bbf35,0xbf0ebec4,
0xbf550000,0xbe483f6d,0x3f7bbf35,0xbf0ebec4,0x3f0ebf80,0xbf7b3ec4,0x3e483f35,0x3f55bf6d,0x3f0ebf80,0xbf7b3ec4,0x3e483f35,0x3f55bf6d,
0x3f558000,0x3e48bf6d,0xbf7b3f35,0x3f0e3ec4,0xbf358000,0xbf353f80,0x3f358000,0x3f35bf80,0xbf353f80,0x3f350000,0x3f35bf80,0xbf350000,
0xbf358000,0xbf353f80,0x3f358000,0x3f35bf80,0xbf353f80,0x3f350000,0x3f35bf80,0xbf350000,0xbf358000,0xbf353f80,0x3f358000,0x3f35bf80,
0xbf353f80,0x3f350000,0x3f35bf80,0xbf350000,0xbf358000,0xbf353f80,0x3f358000,0x3f35bf80,0xbf353f80,0x3f350000,0x3f35bf80,0xbf350000,
0x3f55bf80,0xbe48bec4,0xbf7b3f35,0xbf0e3f6d,0x3f0e8000,0x3f7bbf6d,0x3e48bf35,0xbf553ec4,0x3f0e0000,0x3f7bbf6d,0x3e48bf35,0xbf553ec4,
0xbf553f80,0x3e483ec4,0x3f7bbf35,0x3f0ebf6d,0xbf553f80,0x3e483ec4,0x3f7bbf35,0x3f0ebf6d,0xbf0e8000,0xbf7b3f6d,0xbe483f35,0x3f55bec4,
0xbf0e0000,0xbf7b3f6d,0xbe483f35,0x3f55bec4,0x3f55bf80,0xbe48bec4,0xbf7b3f35,0xbf0e3f6d,0x3ec48000,0x3f6dbf35,0x3f6dbf80,0x3ec4bf35,
0x3f6dbf80,0x3ec4bf35,0xbec40000,0xbf6d3f35,0xbec48000,0xbf6d3f35,0xbf6d3f80,0xbec43f35,0xbf6d3f80,0xbec43f35,0x3ec40000,0x3f6dbf35,
0x3ec48000,0x3f6dbf35,0x3f6dbf80,0x3ec4bf35,0x3f6dbf80,0x3ec4bf35,0xbec40000,0xbf6d3f35,0xbec48000,0xbf6d3f35,0xbf6d3f80,0xbec43f35,
0xbf6d3f80,0xbec43f35,0x3ec40000,0x3f6dbf35,0xbe480000,0xbf0e3ec4,0xbf553f35,0xbf7b3f6d,0x3f7bbf80,0x3f55bf6d,0x3f0ebf35,0x3e48bec4,
0x3f7bbf80,0x3f55bf6d,0x3f0ebf35,0x3e48bec4,0x3e488000,0x3f0ebec4,0x3f55bf35,0x3f7bbf6d,0x3e480000,0x3f0ebec4,0x3f55bf35,0x3f7bbf6d,
0xbf7b3f80,0xbf553f6d,0xbf0e3f35,0xbe483ec4,0xbf7b3f80,0xbf553f6d,0xbf0e3f35,0xbe483ec4,0xbe488000,0xbf0e3ec4,0xbf553f35,0xbf7b3f6d,
0xbf803f80,0xbf803f80,0xbf803f80,0xbf803f80,0x0,0x0,0x0,0x0,0xbf803f80,0xbf803f80,0xbf803f80,0xbf803f80,
0x0,0x0,0x0,0x0,0xbf803f80,0xbf803f80,0xbf803f80,0xbf803f80,0x0,0x0,0x0,0x0,
0xbf803f80,0xbf803f80,0xbf803f80,0xbf803f80,0x0,0x0,0x0,0x0,0xbe480000,0xbf0e3ec4,0xbf553f35,0xbf7b3f6d,
0xbf7b3f80,0xbf553f6d,0xbf0e3f35,0xbe483ec4,0xbf7b3f80,0xbf553f6d,0xbf0e3f35,0xbe483ec4,0x3e480000,0x3f0ebec4,0x3f55bf35,0x3f7bbf6d,
0x3e480000,0x3f0ebec4,0x3f55bf35,0x3f7bbf6d,0x3f7bbf80,0x3f55bf6d,0x3f0ebf35,0x3e48bec4,0x3f7bbf80,0x3f55bf6d,0x3f0ebf35,0x3e48bec4,
0xbe480000,0xbf0e3ec4,0xbf553f35,0xbf7b3f6d,0x3f6dbf80,0x3ec4bf35,0xbec40000,0xbf6d3f35,0x3ec40000,0x3f6dbf35,0x3f6dbf80,0x3ec4bf35,
0xbf6d3f80,0xbec43f35,0x3ec40000,0x3f6dbf35,0xbec40000,0xbf6d3f35,0xbf6d3f80,0xbec43f35,0x3f6dbf80,0x3ec4bf35,0xbec40000,0xbf6d3f35,
0x3ec40000,0x3f6dbf35,0x3f6dbf80,0x3ec4bf35,0xbf6d3f80,0xbec43f35,0x3ec40000,0x3f6dbf35,0xbec40000,0xbf6d3f35,0xbf6d3f80,0xbec43f35,
0x3f55bf80,0xbe48bec4,0xbf7b3f35,0xbf0e3f6d,0xbf0e0000,0xbf7b3f6d,0xbe483f35,0x3f55bec4,0xbf0e0000,0xbf7b3f6d,0xbe483f35,0x3f55bec4,
0xbf553f80,0x3e483ec4,0x3f7bbf35,0x3f0ebf6d,0xbf553f80,0x3e483ec4,0x3f7bbf35,0x3f0ebf6d,0x3f0e0000,0x3f7bbf6d,0x3e48bf35,0xbf553ec4,
0x3f0e0000,0x3f7bbf6d,0x3e48bf35,0xbf553ec4,0x3f55bf80,0xbe48bec4,0xbf7b3f35,0xbf0e3f6d,0xbf353f80,0x3f350000,0x3f35bf80,0xbf350000,
0xbf350000,0xbf353f80,0x3f350000,0x3f35bf80,0xbf353f80,0x3f350000,0x3f35bf80,0xbf350000,0xbf350000,0xbf353f80,0x3f350000,0x3f35bf80,
0xbf353f80,0x3f350000,0x3f35bf80,0xbf350000,0xbf350000,0xbf353f80,0x3f350000,0x3f35bf80,0xbf353f80,0x3f350000,0x3f35bf80,0xbf350000,
0xbf350000,0xbf353f80,0x3f350000,0x3f35bf80,0x3f550000,0x3e48bf6d,0xbf7b3f35,0x3f0e3ec4,0x3f0ebf80,0xbf7b3ec4,0x3e483f35,0x3f55bf6d,
0x3f0ebf80,0xbf7b3ec4,0x3e483f35,0x3f55bf6d,0xbf550000,0xbe483f6d,0x3f7bbf35,0xbf0ebec4,0xbf550000,0xbe483f6d,0x3f7bbf35,0xbf0ebec4,
0xbf0e3f80,0x3f7bbec4,0xbe48bf35,0xbf553f6d,0xbf0e3f80,0x3f7bbec4,0xbe48bf35,0xbf553f6d,0x3f550000,0x3e48bf6d,0xbf7b3f35,0x3f0e3ec4,
0x3ec4bf80,0xbf6d3f35,0x3f6d0000,0xbec4bf35,0x3f6d0000,0xbec4bf35,0xbec43f80,0x3f6dbf35,0xbec43f80,0x3f6dbf35,0xbf6d0000,0x3ec43f35,
0xbf6d0000,0x3ec43f35,0x3ec4bf80,0xbf6d3f35,0x3ec4bf80,0xbf6d3f35,0x3f6d0000,0xbec4bf35,0x3f6d0000,0xbec4bf35,0xbec43f80,0x3f6dbf35,
0xbec43f80,0x3f6dbf35,0xbf6d0000,0x3ec43f35,0xbf6d0000,0x3ec43f35,0x3ec4bf80,0xbf6d3f35,0xbe483f80,0x3f0ebf6d,0xbf553f35,0x3f7bbec4,
0x3f7b0000,0xbf55bec4,0x3f0e3f35,0xbe48bf6d,0x3f7b0000,0xbf55bec4,0x3f0e3f35,0xbe48bf6d,0x3e48bf80,0xbf0e3f6d,0x3f55bf35,0xbf7b3ec4,
0x3e48bf80,0xbf0e3f6d,0x3f55bf35,0xbf7b3ec4,0xbf7b0000,0x3f553ec4,0xbf0ebf35,0x3e483f6d,0xbf7b0000,0x3f553ec4,0xbf0ebf35,0x3e483f6d,
0xbe483f80,0x3f0ebf6d,0xbf553f35,0x3f7bbec4,0x80008000,0x80008000,0x80008000,0x80008000,0xbf803f80,0xbf803f80,0xbf803f80,0xbf803f80,
0x80008000,0x80008000,0x80008000,0x80008000,0xbf803f80,0xbf803f80,0xbf803f80,0xbf803f80,0x80008000,0x80008000,0x80008000,0x80008000,
0xbf803f80,0xbf803f80,0xbf803f80,0xbf803f80,0x80008000,0x80008000,0x80008000,0x80008000,0xbf803f80,0xbf803f80,0xbf803f80,0xbf803f80,
0xbf7b3f80,0xbf553f6d,0xbf0e3f35,0xbe483ec4,0x3e488000,0x3f0ebec4,0x3f55bf35,0x3f7bbf6d,0x3e480000,0x3f0ebec4,0x3f55bf35,0x3f7bbf6d,
0x3f7bbf80,0x3f55bf6d,0x3f0ebf35,0x3e48bec4,0x3f7bbf80,0x3f55bf6d,0x3f0ebf35,0x3e48bec4,0xbe488000,0xbf0e3ec4,0xbf553f35,0xbf7b3f6d,
0xbe480000,0xbf0e3ec4,0xbf553f35,0xbf7b3f6d,0xbf7b3f80,0xbf553f6d,0xbf0e3f35,0xbe483ec4,0xbec48000,0xbf6d3f35,0xbf6d3f80,0xbec43f35,
0x3f6dbf80,0x3ec4bf35,0xbec40000,0xbf6d3f35,0x3ec48000,0x3f6dbf35,0x3f6dbf80,0x3ec4bf35,0xbf6d3f80,0xbec43f35,0x3ec40000,0x3f6dbf35,
0xbec48000,0xbf6d3f35,0xbf6d3f80,0xbec43f35,0x3f6dbf80,0x3ec4bf35,0xbec40000,0xbf6d3f35,0x3ec48000,0x3f6dbf35,0x3f6dbf80,0x3ec4bf35,
0xbf6d3f80,0xbec43f35,0x3ec40000,0x3f6dbf35,0xbf0e0000,0xbf7b3f6d,0xbe483f35,0x3f55bec4,0xbf553f80,0x3e483ec4,0x3f7bbf35,0x3f0ebf6d,
0xbf553f80,0x3e483ec4,0x3f7bbf35,0x3f0ebf6d,0x3f0e8000,0x3f7bbf6d,0x3e48bf35,0xbf553ec4,0x3f0e0000,0x3f7bbf6d,0x3e48bf35,0xbf553ec4,
0x3f55bf80,0xbe48bec4,0xbf7b3f35,0xbf0e3f6d,0x3f55bf80,0xbe48bec4,0xbf7b3f35,0xbf0e3f6d,0xbf0e8000,0xbf7b3f6d,0xbe483f35,0x3f55bec4,
0x3f358000,0x3f35bf80,0xbf358000,0xbf353f80,0xbf353f80,0x3f350000,0x3f35bf80,0xbf350000,0x3f358000,0x3f35bf80,0xbf358000,0xbf353f80,
0xbf353f80,0x3f350000,0x3f35bf80,0xbf350000,0x3f358000,0x3f35bf80,0xbf358000,0xbf353f80,0xbf353f80,0x3f350000,0x3f35bf80,0xbf350000,
0x3f358000,0x3f35bf80,0xbf358000,0xbf353f80,0xbf353f80,0x3f350000,0x3f35bf80,0xbf350000,0x3f0ebf80,0xbf7b3ec4,0x3e483f35,0x3f55bf6d,
0xbf558000,0xbe483f6d,0x3f7bbf35,0xbf0ebec4,0xbf550000,0xbe483f6d,0x3f7bbf35,0xbf0ebec4,0xbf0e3f80,0x3f7bbec4,0xbe48bf35,0xbf553f6d,
0xbf0e3f80,0x3f7bbec4,0xbe48bf35,0xbf553f6d,0x3f558000,0x3e48bf6d,0xbf7b3f35,0x3f0e3ec4,0x3f550000,0x3e48bf6d,0xbf7b3f35,0x3f0e3ec4,
0x3f0ebf80,0xbf7b3ec4,0x3e483f35,0x3f55bf6d,0xbf6d8000,0x3ec43f35,0x3ec4bf80,0xbf6d3f35,0x3ec4bf80,0xbf6d3f35,0x3f6d0000,0xbec4bf35,
0x3f6d8000,0xbec4bf35,0xbec43f80,0x3f6dbf35,0xbec43f80,0x3f6dbf35,0xbf6d0000,0x3ec43f35,0xbf6d8000,0x3ec43f35,0x3ec4bf80,0xbf6d3f35,
0x3ec4bf80,0xbf6d3f35,0x3f6d0000,0xbec4bf35,0x3f6d8000,0xbec4bf35,0xbec43f80,0x3f6dbf35,0xbec43f80,0x3f6dbf35,0xbf6d0000,0x3ec43f35,
0x3f7b0000,0xbf55bec4,0x3f0e3f35,0xbe48bf6d,0x3e48bf80,0xbf0e3f6d,0x3f55bf35,0xbf7b3ec4,0x3e48bf80,0xbf0e3f6d,0x3f55bf35,0xbf7b3ec4,
0xbf7b8000,0x3f553ec4,0xbf0ebf35,0x3e483f6d,0xbf7b0000,0x3f553ec4,0xbf0ebf35,0x3e483f6d,0xbe483f80,0x3f0ebf6d,0xbf553f35,0x3f7bbec4,
0xbe483f80,0x3f0ebf6d,0xbf553f35,0x3f7bbec4,0x3f7b8000,0xbf55bec4,0x3f0e3f35,0xbe48bf6d,0x3f80,0xbf80,0x3f80,0xbf80,
0xbf800000,0x3f800000,0xbf800000,0x3f800000,0x3f80,0xbf80,0x3f80,0xbf80,0xbf800000,0x3f800000,0xbf800000,0x3f800000,
0x3f80,0xbf80,0x3f80,0xbf80,0xbf800000,0x3f800000,0xbf800000,0x3f800000,0x3f80,0xbf80,0x3f80,0xbf80,
0xbf800000,0x3f800000,0xbf800000,0x3f800000,0xbf7b0000,0x3f55bec4,0xbf0e3f35,0x3e48bf6d,0x3e483f80,0xbf0ebf6d,0x3f553f35,0xbf7bbec4,
0x3e483f80,0xbf0ebf6d,0x3f553f35,0xbf7bbec4,0x3f7b0000,0xbf553ec4,0x3f0ebf35,0xbe483f6d,0x3f7b0000,0xbf553ec4,0x3f0ebf35,0xbe483f6d,
0xbe48bf80,0x3f0e3f6d,0xbf55bf35,0x3f7b3ec4,0xbe48bf80,0x3f0e3f6d,0xbf55bf35,0x3f7b3ec4,0xbf7b0000,0x3f55bec4,0xbf0e3f35,0x3e48bf6d,
0xbec4bf80,0x3f6d3f35,0xbf6d0000,0x3ec4bf35,0x3f6d0000,0xbec43f35,0xbec4bf80,0x3f6d3f35,0x3ec43f80,0xbf6dbf35,0x3f6d0000,0xbec43f35,
0xbf6d0000,0x3ec4bf35,0x3ec43f80,0xbf6dbf35,0xbec4bf80,0x3f6d3f35,0xbf6d0000,0x3ec4bf35,0x3f6d0000,0xbec43f35,0xbec4bf80,0x3f6d3f35,
0x3ec43f80,0xbf6dbf35,0x3f6d0000,0xbec43f35,0xbf6d0000,0x3ec4bf35,0x3ec43f80,0xbf6dbf35,0xbf0ebf80,0x3f7b3ec4,0xbe483f35,0xbf55bf6d,
0xbf550000,0xbe48bf6d,0x3f7b3f35,0xbf0e3ec4,0xbf550000,0xbe48bf6d,0x3f7b3f35,0xbf0e3ec4,0x3f0e3f80,0xbf7bbec4,0x3e48bf35,0x3f553f6d,
0x3f0e3f80,0xbf7bbec4,0x3e48bf35,0x3f553f6d,0x3f550000,0x3e483f6d,0xbf7bbf35,0x3f0ebec4,0x3f550000,0x3e483f6d,0xbf7bbf35,0x3f0ebec4,
0xbf0ebf80,0x3f7b3ec4,0xbe483f35,0xbf55bf6d,0x3f353f80,0xbf350000,0xbf35bf80,0x3f350000,0xbf350000,0xbf35bf80,0x3f350000,0x3f353f80,
0x3f353f80,0xbf350000,0xbf35bf80,0x3f350000,0xbf350000,0xbf35bf80,0x3f350000,0x3f353f80,0x3f353f80,0xbf350000,0xbf35bf80,0x3f350000,
0xbf350000,0xbf35bf80,0x3f350000,0x3f353f80,0x3f353f80,0xbf350000,0xbf35bf80,0x3f350000,0xbf350000,0xbf35bf80,0x3f350000,0x3f353f80,
0x3f0e0000,0x3f7b3f6d,0x3e483f35,0xbf55bec4,0xbf55bf80,0x3e48bec4,0x3f7b3f35,0x3f0e3f6d,0xbf55bf80,0x3e48bec4,0x3f7b3f35,0x3f0e3f6d,
0xbf0e0000,0xbf7bbf6d,0xbe48bf35,0x3f553ec4,0xbf0e0000,0xbf7bbf6d,0xbe48bf35,0x3f553ec4,0x3f553f80,0xbe483ec4,0xbf7bbf35,0xbf0ebf6d,
0x3f553f80,0xbe483ec4,0xbf7bbf35,0xbf0ebf6d,0x3f0e0000,0x3f7b3f6d,0x3e483f35,0xbf55bec4,0xbf6dbf80,0xbec4bf35,0x3ec40000,0x3f6d3f35,
0x3ec40000,0x3f6d3f35,0x3f6d3f80,0x3ec43f35,0x3f6d3f80,0x3ec43f35,0xbec40000,0xbf6dbf35,0xbec40000,0xbf6dbf35,0xbf6dbf80,0xbec4bf35,
0xbf6dbf80,0xbec4bf35,0x3ec40000,0x3f6d3f35,0x3ec40000,0x3f6d3f35,0x3f6d3f80,0x3ec43f35,0x3f6d3f80,0x3ec43f35,0xbec40000,0xbf6dbf35,
0xbec40000,0xbf6dbf35,0xbf6dbf80,0xbec4bf35,0x3f7b3f80,0x3f553f6d,0x3f0e3f35,0x3e483ec4,0x3e480000,0x3f0e3ec4,0x3f553f35,0x3f7b3f6d,
0x3e480000,0x3f0e3ec4,0x3f553f35,0x3f7b3f6d,0xbf7bbf80,0xbf55bf6d,0xbf0ebf35,0xbe48bec4,0xbf7bbf80,0xbf55bf6d,0xbf0ebf35,0xbe48bec4,
0xbe480000,0xbf0ebec4,0xbf55bf35,0xbf7bbf6d,0xbe480000,0xbf0ebec4,0xbf55bf35,0xbf7bbf6d,0x3f7b3f80,0x3f553f6d,0x3f0e3f35,0x3e483ec4,
0x3f808000,0xbf808000,0x3f808000,0xbf808000,0x3f80,0xbf80,0x3f80,0xbf80,0x3f808000,0xbf808000,0x3f808000,0xbf808000,
0x3f80,0xbf80,0x3f80,0xbf80,0x3f808000,0xbf808000,0x3f808000,0xbf808000,0x3f80,0xbf80,0x3f80,0xbf80,
0x3f808000,0xbf808000,0x3f808000,0xbf808000,0x3f80,0xbf80,0x3f80,0xbf80,0x3e483f80,0xbf0ebf6d,0x3f553f35,0xbf7bbec4,
0x3f7b8000,0xbf553ec4,0x3f0ebf35,0xbe483f6d,0x3f7b0000,0xbf553ec4,0x3f0ebf35,0xbe483f6d,0xbe48bf80,0x3f0e3f6d,0xbf55bf35,0x3f7b3ec4,
0xbe48bf80,0x3f0e3f6d,0xbf55bf35,0x3f7b3ec4,0xbf7b8000,0x3f55bec4,0xbf0e3f35,0x3e48bf6d,0xbf7b0000,0x3f55bec4,0xbf0e3f35,0x3e48bf6d,
0x3e483f80,0xbf0ebf6d,0x3f553f35,0xbf7bbec4,0xbf6d8000,0x3ec4bf35,0x3ec43f80,0xbf6dbf35,0xbec4bf80,0x3f6d3f35,0xbf6d0000,0x3ec4bf35,
0x3f6d8000,0xbec43f35,0xbec4bf80,0x3f6d3f35,0x3ec43f80,0xbf6dbf35,0x3f6d0000,0xbec43f35,0xbf6d8000,0x3ec4bf35,0x3ec43f80,0xbf6dbf35,
0xbec4bf80,0x3f6d3f35,0xbf6d0000,0x3ec4bf35,0x3f6d8000,0xbec43f35,0xbec4bf80,0x3f6d3f35,0x3ec43f80,0xbf6dbf35,0x3f6d0000,0xbec43f35,
0xbf550000,0xbe48bf6d,0x3f7b3f35,0xbf0e3ec4,0x3f0e3f80,0xbf7bbec4,0x3e48bf35,0x3f553f6d,0x3f0e3f80,0xbf7bbec4,0x3e48bf35,0x3f553f6d,
0x3f558000,0x3e483f6d,0xbf7bbf35,0x3f0ebec4,0x3f550000,0x3e483f6d,0xbf7bbf35,0x3f0ebec4,0xbf0ebf80,0x3f7b3ec4,0xbe483f35,0xbf55bf6d,
0xbf0ebf80,0x3f7b3ec4,0xbe483f35,0xbf55bf6d,0xbf558000,0xbe48bf6d,0x3f7b3f35,0xbf0e3ec4,0x3f358000,0x3f353f80,0xbf358000,0xbf35bf80,
0x3f353f80,0xbf350000,0xbf35bf80,0x3f350000,0x3f358000,0x3f353f80,0xbf358000,0xbf35bf80,0x3f353f80,0xbf350000,0xbf35bf80,0x3f350000,
0x3f358000,0x3f353f80,0xbf358000,0xbf35bf80,0x3f353f80,0xbf350000,0xbf35bf80,0x3f350000,0x3f358000,0x3f353f80,0xbf358000,0xbf35bf80,
0x3f353f80,0xbf350000,0xbf35bf80,0x3f350000,0xbf55bf80,0x3e48bec4,0x3f7b3f35,0x3f0e3f6d,0xbf0e8000,0xbf7bbf6d,0xbe48bf35,0x3f553ec4,
0xbf0e0000,0xbf7bbf6d,0xbe48bf35,0x3f553ec4,0x3f553f80,0xbe483ec4,0xbf7bbf35,0xbf0ebf6d,0x3f553f80,0xbe483ec4,0xbf7bbf35,0xbf0ebf6d,
0x3f0e8000,0x3f7b3f6d,0x3e483f35,0xbf55bec4,0x3f0e0000,0x3f7b3f6d,0x3e483f35,0xbf55bec4,0xbf55bf80,0x3e48bec4,0x3f7b3f35,0x3f0e3f6d,
0xbec48000,0xbf6dbf35,0xbf6dbf80,0xbec4bf35,0xbf6dbf80,0xbec4bf35,0x3ec40000,0x3f6d3f35,0x3ec48000,0x3f6d3f35,0x3f6d3f80,0x3ec43f35,
0x3f6d3f80,0x3ec43f35,0xbec40000,0xbf6dbf35,0xbec48000,0xbf6dbf35,0xbf6dbf80,0xbec4bf35,0xbf6dbf80,0xbec4bf35,0x3ec40000,0x3f6d3f35,
0x3ec48000,0x3f6d3f35,0x3f6d3f80,0x3ec43f35,0x3f6d3f80,0x3ec43f35,0xbec40000,0xbf6dbf35,0x3e480000,0x3f0e3ec4,0x3f553f35,0x3f7b3f6d,
0xbf7bbf80,0xbf55bf6d,0xbf0ebf35,0xbe48bec4,0xbf7bbf80,0xbf55bf6d,0xbf0ebf35,0xbe48bec4,0xbe488000,0xbf0ebec4,0xbf55bf35,0xbf7bbf6d,
0xbe480000,0xbf0ebec4,0xbf55bf35,0xbf7bbf6d,0x3f7b3f80,0x3f553f6d,0x3f0e3f35,0x3e483ec4,0x3f7b3f80,0x3f553f6d,0x3f0e3f35,0x3e483ec4,
0x3e488000,0x3f0e3ec4,0x3f553f35,0x3f7b3f6d,
};
__device__ __align__(1024) uint8_t g_hT[32 * 262144];
__device__ __align__(1024) bf16 g_U[128 * 2 * 8 * 1024];
__device__ __align__(128) float g_gp[128 * 256];
__device__ __align__(128) uint4 g_agg[16 * 512];
#define CS 32
#define NREP 1
#define NREPH 4
constexpr int RS = 9 * CS;
__device__ __align__(128) unsigned g_cnt[32 * RS];
constexpr int CNT_U = 0, CNT_V = 1, CNT_DONE = 2, CNT_EPOCH = 3, CNT_H = 4  ;
#define PROFK(i) do { } while (0)
#define PROFC(i) do { } while (0)
#define PROF(i) do { } while (0)
#define PROFX(i) do { } while (0)
#define PROFR(i) do { } while (0)
#define PROFT(i) do { } while (0)
#define PROFS(i) do { } while (0)
#define PROFG(i) do { } while (0)

constexpr int SLOT = 32768;
constexpr int OFF_HS = 4 * SLOT;
constexpr int OFF_W = OFF_HS + 16384;
constexpr int OFF_F = OFF_W + 2 * 18432;
constexpr int OFF_G = OFF_F + 8192;
constexpr int OFF_K = OFF_G + 1024;
constexpr int OFF_GW = OFF_K + 2048;
constexpr int OFF_U = 6 * SLOT;
constexpr int OFF_BAR = OFF_U + 32768;
constexpr int OFF_SC = OFF_BAR + 384;
constexpr int OFF_KEPT = OFF_SC + 1024;
constexpr int OFF_PROF = OFF_KEPT + 64;
constexpr int SMEM_BYTES = OFF_PROF;
constexpr int BAR_FULL = 0  , BAR_U = 11, BAR_W = 12  , BAR_F = 14  ,
              BAR_EMPTY = 17  , BAR_HW = 22  , BAR_WR = 25, BAR_VW = 26, BAR_S1 = 27,
              BAR_XC = 28  , BAR_HR = 32,
              BAR_C = 34  , BAR_HD = 36  ;

#define DEVI __device__ __forceinline__
constexpr unsigned SPIN_LIMIT = 1u << 22;

DEVI uint32_t smem_u32(const void* p) { return (uint32_t)__cvta_generic_to_shared(p); }
DEVI uint64_t gtime() { uint64_t t; asm volatile("mov.u64 %0, %%globaltimer;" : "=l"(t)); return t; }
DEVI void mbar_init(uint32_t bar, uint32_t cnt) { asm volatile("mbarrier.init.shared::cta.b64 [%0], %1;" :: "r"(bar), "r"(cnt) : "memory"); }
DEVI void mbar_expect_tx(uint32_t bar, uint32_t bytes) { asm volatile("mbarrier.arrive.expect_tx.shared::cta.b64 _, [%0], %1;" :: "r"(bar), "r"(bytes) : "memory"); }
DEVI void mbar_arrive(uint32_t bar) { asm volatile("mbarrier.arrive.shared::cta.b64 _, [%0];" :: "r"(bar) : "memory"); }
#define WAIT_LOOP "{\n.reg .pred p;\n.reg .u32 n;\nmov.u32 n, 0;\n" \
                  "LW:\nmbarrier.try_wait.parity.shared::cta.b64 p, [%0], %1;\n@p bra LD;\n" \
                  "add.u32 n, n, 1;\nsetp.lt.u32 p, n, 131072;\n@p bra LW;\nLD:\n"
DEVI void mbar_wait(uint32_t bar, uint32_t parity) { asm volatile(WAIT_LOOP "}" :: "r"(bar), "r"(parity) : "memory"); }
DEVI void warp_arrive(uint32_t bar) { asm volatile("{\n.reg .pred p;\nelect.sync _|p, 0xffffffff;\n@p mbarrier.arrive.shared::cta.b64 _, [%0];\n}" :: "r"(bar) : "memory"); }
DEVI bool elect() {
    uint32_t p;
    asm volatile("{\n.reg .pred P;\nelect.sync _|P, 0xffffffff;\nselp.u32 %0, 1, 0, P;\n}" : "=r"(p));
    return p;
}
DEVI void fence_barrier_init() { asm volatile("fence.mbarrier_init.release.cluster;" ::: "memory"); }
DEVI void fence_proxy_async_smem() { asm volatile("fence.proxy.async.shared::cta;" ::: "memory"); }
#define HF 1
#define FPOS 0
DEVI void helper_sync() { asm volatile("bar.sync 1, 128;" ::: "memory"); }

DEVI void pause(unsigned n) {
    asm volatile("{\n.reg .pred p;\n.reg .u32 a, b;\nmov.u32 a, %%clock;\n"
                 "LP:\nmov.u32 b, %%clock;\nsub.u32 b, b, a;\nsetp.lt.u32 p, b, %0;\n@p bra LP;\n}" :: "r"(n) : "memory");
}
DEVI void sched_fence() { asm volatile("{\n.reg .pred p;\n.reg .b32 n;\nLP:\nactivemask.b32 n;\nsetp.eq.u32 p, n, 0;\n@p bra LP;\n}" ::: "memory"); }
#define P_POLL 0
#define NPOLL 1
DEVI void wait_counter(const unsigned* p, unsigned target) {
    unsigned v[NPOLL];
    auto ld = [&](int i) { asm volatile("ld.relaxed.gpu.global.u32 %0, [%1];" : "=r"(v[i]) : "l"(p) : "memory"); };
#pragma unroll
    for (int i = 0; i < NPOLL; i++) { if (i) pause(200); ld(i); }
#pragma unroll 1
    for (unsigned n = 0; n < SPIN_LIMIT; n++) {
#pragma unroll
        for (int i = 0; i < NPOLL; i++) {
            if ((int)(v[i] - target) >= 0) return;
            if (P_POLL) pause(P_POLL);
            ld(i);
        }
    }
}
DEVI void signal_counter(unsigned* p) {
#pragma unroll
    for (int r = 0; r < NREP; r++) asm volatile("red.relaxed.gpu.global.add.u32 [%0], 1;" :: "l"(p + r * RS) : "memory");
}

DEVI void tma_load_3d(uint32_t dst, const CUtensorMap* map, uint32_t bar, int c0, int c1, int c2) {
    asm volatile("cp.async.bulk.tensor.3d.shared::cluster.global.mbarrier::complete_tx::bytes [%0], [%1, {%3, %4, %5}], [%2];"
        :: "r"(dst), "l"(map), "r"(bar), "r"(c0), "r"(c1), "r"(c2) : "memory");
}
DEVI void tma_load_4d(uint32_t dst, const CUtensorMap* map, uint32_t bar, int c0, int c1, int c2, int c3) {
    asm volatile("cp.async.bulk.tensor.4d.shared::cluster.global.mbarrier::complete_tx::bytes [%0], [%1, {%3, %4, %5, %6}], [%2];"
        :: "r"(dst), "l"(map), "r"(bar), "r"(c0), "r"(c1), "r"(c2), "r"(c3) : "memory");
}
DEVI void tma_load_5d(uint32_t dst, const CUtensorMap* map, uint32_t bar, int c0, int c3, int c4) {
    asm volatile("cp.async.bulk.tensor.5d.shared::cluster.global.mbarrier::complete_tx::bytes [%0], [%1, {%3, %6, %6, %4, %5}], [%2];"
        :: "r"(dst), "l"(map), "r"(bar), "r"(c0), "r"(c3), "r"(c4), "r"(0) : "memory");
}
DEVI void tma_store_4d(const CUtensorMap* map, uint32_t src, int c0, int c1, int c2, int c3) {
    asm volatile("cp.async.bulk.tensor.4d.global.shared::cta.bulk_group [%0, {%2, %3, %4, %5}], [%1];"
        :: "l"(map), "r"(src), "r"(c0), "r"(c1), "r"(c2), "r"(c3) : "memory");
}
DEVI void bulk_load(uint32_t dst, const void* src, uint32_t bytes, uint32_t bar) {
    asm volatile("cp.async.bulk.shared::cluster.global.mbarrier::complete_tx::bytes [%0], [%1], %2, [%3];"
        :: "r"(dst), "l"(src), "r"(bytes), "r"(bar) : "memory");
}
DEVI void bulk_prefetch_l2(const void* src, uint32_t bytes) {
    asm volatile("cp.async.bulk.prefetch.L2.global [%0], %1;" :: "l"(src), "r"(bytes) : "memory");
}
DEVI void tma_store_3d(const CUtensorMap* map, uint32_t src, int c0, int c1, int c2) {
    asm volatile("cp.async.bulk.tensor.3d.global.shared::cta.bulk_group [%0, {%2, %3, %4}], [%1];"
        :: "l"(map), "r"(src), "r"(c0), "r"(c1), "r"(c2) : "memory");
}
DEVI void bulk_store(void* dst, uint32_t src, uint32_t bytes) {
    asm volatile("cp.async.bulk.global.shared::cta.bulk_group [%0], [%1], %2;" :: "l"(dst), "r"(src), "r"(bytes) : "memory");
}
DEVI void bulk_commit() { asm volatile("cp.async.bulk.commit_group;" ::: "memory"); }
DEVI void bulk_wait0() { asm volatile("cp.async.bulk.wait_group 0;" ::: "memory"); }

DEVI void wgmma_fence() { asm volatile("wgmma.fence.sync.aligned;" ::: "memory"); }
DEVI void wgmma_commit() { asm volatile("wgmma.commit_group.sync.aligned;" ::: "memory"); }
template<int N> DEVI void wgmma_wait() { asm volatile("wgmma.wait_group.sync.aligned %0;" :: "n"(N) : "memory"); }
template<int N> DEVI void wgmma_wait_all(float (&d)[N]) {
    wgmma_wait<0>();
#pragma unroll
    for (int i = 0; i < N; i++) asm volatile("" : "+f"(d[i]) :: "memory");
}
template<int R> DEVI void reg_alloc() { asm volatile("setmaxnreg.inc.sync.aligned.u32 %0;" :: "n"(R)); }
template<int R> DEVI void reg_dealloc() { asm volatile("setmaxnreg.dec.sync.aligned.u32 %0;" :: "n"(R)); }

constexpr uint32_t SB0 = 1024;
DEVI uint64_t make_desc(uint32_t off, uint32_t lbo, uint32_t sbo, uint32_t mode = 1) {
    return (uint64_t)(((SB0 + off) >> 4) | ((lbo >> 4) << 16)) | ((uint64_t)((sbo >> 4) | (mode << 30)) << 32);
}

#define ACC8(a, o) "+f"(a[o+0]), "+f"(a[o+1]), "+f"(a[o+2]), "+f"(a[o+3]), "+f"(a[o+4]), "+f"(a[o+5]), "+f"(a[o+6]), "+f"(a[o+7])
#define OUT8(a, o) "=f"(a[o+0]), "=f"(a[o+1]), "=f"(a[o+2]), "=f"(a[o+3]), "=f"(a[o+4]), "=f"(a[o+5]), "=f"(a[o+6]), "=f"(a[o+7])
#define ACC32(a, o) ACC8(a, o), ACC8(a, o+8), ACC8(a, o+16), ACC8(a, o+24)

#define SS_N128 "{\n.reg .pred p;\nsetp.ne.b32 p, %66, 0;\n" \
        "wgmma.mma_async.sync.aligned.m64n128k16.f32.bf16.bf16 " \
        "{%0, %1, %2, %3, %4, %5, %6, %7, %8, %9, %10, %11, %12, %13, %14, %15, " \
        "%16, %17, %18, %19, %20, %21, %22, %23, %24, %25, %26, %27, %28, %29, %30, %31, " \
        "%32, %33, %34, %35, %36, %37, %38, %39, %40, %41, %42, %43, %44, %45, %46, %47, " \
        "%48, %49, %50, %51, %52, %53, %54, %55, %56, %57, %58, %59, %60, %61, %62, %63}, " \
        "%64, %65, p, 1, 1, %67, %68;\n}\n"
template<int TA, int TB>
DEVI void wgmma_n128(float (&d)[64], uint64_t da, uint64_t db, int scale_d) {
    asm volatile(SS_N128 : ACC32(d, 0), ACC32(d, 32) : "l"(da), "l"(db), "r"(scale_d), "n"(TA), "n"(TB));
}
DEVI void wgmma_n128_set(float (&d)[64], uint64_t da, uint64_t db) {
    asm volatile(SS_N128 : OUT8(d, 0), OUT8(d, 8), OUT8(d, 16), OUT8(d, 24), OUT8(d, 32), OUT8(d, 40), OUT8(d, 48), OUT8(d, 56) : "l"(da), "l"(db), "n"(0), "n"(0), "n"(1));
}
#define SS_N16 "{\n.reg .pred p;\nsetp.ne.b32 p, 0, 0;\n" \
        "wgmma.mma_async.sync.aligned.m64n16k16.f32.bf16.bf16 " \
        "{%0, %1, %2, %3, %4, %5, %6, %7}, %8, %9, p, 1, 1, %10, 0;\n}\n"
template<int TA> DEVI void wgmma_n16(float* d, uint64_t da, uint64_t db) {
    asm volatile(SS_N16 : OUT8(d, 0) : "l"(da), "l"(db), "n"(TA));
}
#define SS_N8 "{\n.reg .pred p;\nsetp.ne.b32 p, %6, 0;\n" \
        "wgmma.mma_async.sync.aligned.m64n8k16.f32.bf16.bf16 {%0, %1, %2, %3}, %4, %5, p, 1, 1, 0, 0;\n}\n"
DEVI void wgmma_n8(float (&d)[4], uint64_t da, uint64_t db, bool add) {
    if (add) asm volatile(SS_N8 : "+f"(d[0]), "+f"(d[1]), "+f"(d[2]), "+f"(d[3]) : "l"(da), "l"(db), "n"(1));
    else asm volatile(SS_N8 : "=f"(d[0]), "=f"(d[1]), "=f"(d[2]), "=f"(d[3]) : "l"(da), "l"(db), "n"(0));
}
#define RS_N64 "{\n.reg .pred p;\nsetp.ne.b32 p, %37, 0;\n" \
        "wgmma.mma_async.sync.aligned.m64n64k16.f32.bf16.bf16 " \
        "{%0, %1, %2, %3, %4, %5, %6, %7, %8, %9, %10, %11, %12, %13, %14, %15, " \
        "%16, %17, %18, %19, %20, %21, %22, %23, %24, %25, %26, %27, %28, %29, %30, %31}, " \
        "{%32, %33, %34, %35}, %36, p, 1, 1, %38;\n}\n"
template<int SCALE_D, int TB = 0>
DEVI void wgmma_rs_n64(float (&d)[32], const uint32_t (&a)[4], uint64_t db) {
    if (SCALE_D) asm volatile(RS_N64 : ACC32(d, 0) : "r"(a[0]), "r"(a[1]), "r"(a[2]), "r"(a[3]), "l"(db), "n"(1), "n"(TB));
    else asm volatile(RS_N64 : OUT8(d, 0), OUT8(d, 8), OUT8(d, 16), OUT8(d, 24) : "r"(a[0]), "r"(a[1]), "r"(a[2]), "r"(a[3]), "l"(db), "n"(0), "n"(TB));
}
#define SS_N64 "{\n.reg .pred p;\nsetp.ne.b32 p, %34, 0;\n" \
        "wgmma.mma_async.sync.aligned.m64n64k16.f32.bf16.bf16 " \
        "{%0, %1, %2, %3, %4, %5, %6, %7, %8, %9, %10, %11, %12, %13, %14, %15, " \
        "%16, %17, %18, %19, %20, %21, %22, %23, %24, %25, %26, %27, %28, %29, %30, %31}, " \
        "%32, %33, p, 1, 1, 0, 1;\n}\n"
template<int SCALE_D> DEVI void wgmma_ss_n64(float (&d)[32], uint64_t da, uint64_t db) {
    if (SCALE_D) asm volatile(SS_N64 : ACC32(d, 0) : "l"(da), "l"(db), "n"(1));
    else asm volatile(SS_N64 : OUT8(d, 0), OUT8(d, 8), OUT8(d, 16), OUT8(d, 24) : "l"(da), "l"(db), "n"(0));
}
DEVI void ldsm_x4_t(uint32_t (&r)[4], uint32_t addr) {
    asm volatile("ldmatrix.sync.aligned.m8n8.x4.trans.shared.b16 {%0, %1, %2, %3}, [%4];"
        : "=r"(r[0]), "=r"(r[1]), "=r"(r[2]), "=r"(r[3]) : "r"(addr) : "memory");
}
DEVI void ldsm_x4(uint32_t (&r)[4], uint32_t addr) {
    asm volatile("ldmatrix.sync.aligned.m8n8.x4.shared.b16 {%0, %1, %2, %3}, [%4];"
        : "=r"(r[0]), "=r"(r[1]), "=r"(r[2]), "=r"(r[3]) : "r"(addr) : "memory");
}
DEVI void stsm_x4(uint32_t addr, uint32_t r0, uint32_t r1, uint32_t r2, uint32_t r3) {
    asm volatile("stmatrix.sync.aligned.m8n8.x4.shared.b16 [%0], {%1, %2, %3, %4};"
        :: "r"(addr), "r"(r0), "r"(r1), "r"(r2), "r"(r3) : "memory");
}
DEVI void stsm_x4_t(uint32_t addr, uint32_t r0, uint32_t r1, uint32_t r2, uint32_t r3) {
    asm volatile("stmatrix.sync.aligned.m8n8.x4.trans.shared.b16 [%0], {%1, %2, %3, %4};"
        :: "r"(addr), "r"(r0), "r"(r1), "r"(r2), "r"(r3) : "memory");
}
DEVI uint32_t movm(uint32_t a) { uint32_t d; asm volatile("movmatrix.sync.aligned.m8n8.trans.b16 %0, %1;" : "=r"(d) : "r"(a)); return d; }
DEVI uint32_t pack2(float lo, float hi) { uint32_t d; asm("cvt.rn.bf16x2.f32 %0, %1, %2;" : "=r"(d) : "f"(hi), "f"(lo)); return d; }
DEVI float bf_lo(uint32_t v) { return __uint_as_float(v << 16); }
DEVI float bf_hi(uint32_t v) { return __uint_as_float(v & 0xffff0000u); }
DEVI float bf_round(float v) { return __bfloat162float(__float2bfloat16_rn(v)); }
DEVI uint32_t bf_mul2(uint32_t a, uint32_t b) { uint32_t d; asm("mul.rn.bf16x2 %0, %1, %2;" : "=r"(d) : "r"(a), "r"(b)); return d; }
DEVI uint32_t bf_add2(uint32_t a, uint32_t b) { uint32_t d; asm("add.rn.bf16x2 %0, %1, %2;" : "=r"(d) : "r"(a), "r"(b)); return d; }
DEVI uint32_t bf_sub2(uint32_t a, uint32_t b) { uint32_t d; asm("sub.rn.bf16x2 %0, %1, %2;" : "=r"(d) : "r"(a), "r"(b)); return d; }
DEVI uint4 lds128u(uint32_t a) { uint4 v; asm volatile("ld.shared.v4.u32 {%0, %1, %2, %3}, [%4];" : "=r"(v.x), "=r"(v.y), "=r"(v.z), "=r"(v.w) : "r"(a) : "memory"); return v; }
DEVI void sts128u(uint32_t a, uint32_t x, uint32_t y, uint32_t z, uint32_t w) { asm volatile("st.shared.v4.u32 [%0], {%1, %2, %3, %4};" :: "r"(a), "r"(x), "r"(y), "r"(z), "r"(w) : "memory"); }
DEVI uint2 lds64u(uint32_t a) { uint2 v; asm volatile("ld.shared.v2.u32 {%0, %1}, [%2];" : "=r"(v.x), "=r"(v.y) : "r"(a) : "memory"); return v; }
DEVI uint32_t ldg32u(const void* p) { uint32_t v; asm volatile("ld.global.nc.u32 %0, [%1];" : "=r"(v) : "l"(p) : "memory"); return v; }
DEVI void sts64(uint32_t a, float x, float y) { asm volatile("st.shared.v2.f32 [%0], {%1, %2};" :: "r"(a), "f"(x), "f"(y) : "memory"); }
DEVI void sts32(uint32_t a, uint32_t v) { asm volatile("st.shared.u32 [%0], %1;" :: "r"(a), "r"(v) : "memory"); }
DEVI uint32_t lds16(uint32_t a) { uint32_t v; asm volatile("ld.shared.u16 %0, [%1];" : "=r"(v) : "r"(a) : "memory"); return v; }
DEVI void cmul2(uint32_t& x, uint32_t& y, uint32_t c, uint32_t s, uint32_t n) {
    asm("{\n.reg .b32 t, u;\nmul.rn.bf16x2 t, %1, %4;\nmul.rn.bf16x2 u, %1, %2;\n"
        "fma.rn.bf16x2 %1, %0, %3, u;\nfma.rn.bf16x2 %0, %0, %2, t;\n}" : "+r"(x), "+r"(y) : "r"(c), "r"(s), "r"(n));
}
DEVI uint32_t neg2(uint32_t s) { uint32_t n; asm volatile("xor.b32 %0, %1, 0x80008000;" : "=r"(n) : "r"(s)); return n; }
DEVI void cmul2(uint32_t& x, uint32_t& y, uint32_t c, uint32_t s) { cmul2(x, y, c, s, neg2(s)); }
DEVI void cmul2c(uint32_t& x, uint32_t& y, uint32_t c, uint32_t s) { cmul2(x, y, c, neg2(s), s); }
DEVI void sts16(uint32_t a, float v) { asm volatile("st.shared.u16 [%0], %1;" :: "r"(a), "r"(pack2(v, v)) : "memory"); }

DEVI float2 cmul(float2 a, float2 b) { return make_float2(fmaf(a.x, b.x, -a.y * b.y), fmaf(a.x, b.y, a.y * b.x)); }
DEVI float2 cfma(float2 a, float2 b, float2 c) { return make_float2(fmaf(a.x, b.x, fmaf(-a.y, b.y, c.x)), fmaf(a.x, b.y, fmaf(a.y, b.x, c.y))); }

DEVI float2 csq(float2 a) {
    float y;
    asm("{\n.reg .f32 t;\nmul.ftz.f32 t, %1, %2;\nmul.ftz.f32 %0, t, 0f40000000;\n}" : "=f"(y) : "f"(a.x), "f"(a.y));
    return make_float2(fmaf(a.x, a.x, -a.y * a.y), y);
}

struct Params {
    const bf16 *lam_re, *lam_im, *log_dt, *dskip, *gate_w, *c_re, *c_im, *b_re, *b_im, *x;
    int swapB;
};

#define P_W0 0
#define P_W1 0
#define P_R8F 0
#define P_R8I 0
#define P_CF 0
#define P_S1 0
#define P_SK 0
#define R8_POLL 8
#define R8B 1
#define SCB 32
#define C0 1
#define R8A 4
DEVI void radix8(uint32_t sb, bool inv, int w, int lane, int bar) {
    const uint64_t dg = make_desc(OFF_G + (inv ? 512 : 0), 128, 256, 0), da = make_desc(OFF_U, 16, 16384);
    float acc[2][64];
    wgmma_fence();
#pragma unroll
    for (int j = 0; j < 8; j++) wgmma_n16<1>(acc[0] + 8 * j, da + 64 * j, dg);
    wgmma_commit();
    sched_fence();
    asm volatile("" : "+r"(lane));
    const int kk = lane & 7, ch = 2 * w + ((lane >> 3) & 1);
    const uint32_t st = sb + OFF_U + (inv ? (lane >> 4) * 16384 + kk * 128 + ((ch ^ kk) << 4)
        : (kk & 1) * 16384 + (kk >> 2) * 2048 + (lane >> 4) * 1024 + (w >> 1) * 128 + ((((kk & 2) * 2 + ((ch & 3) ^ (kk >> 2) ^ (2 * (kk & 1)))) ^ (w >> 1)) << 4));
    uint32_t sa[4];
#pragma unroll
    for (int i = 0; i < 4; i++) { sa[i] = inv ? (st ^ (i << 4)) + i * 1024 : (st ^ (i << 5)) + i * 256; asm volatile("" : "+r"(sa[i])); }
    const int warp = inv;
    sched_fence();
    if (R8A) {
        wgmma_fence();
#pragma unroll
        for (int j = 0; j < R8A; j++) wgmma_n16<1>(acc[1] + 8 * j, da + 64 * (8 + j), dg);
        wgmma_commit();
    }
    PROFC(8);
#pragma unroll
    for (int i = 0; i < 2; i++) {
        if (i || !R8A) wgmma_wait<0>(); else wgmma_wait<1>();
#pragma unroll
        for (int j = 0; j < 64; j++) asm volatile("" : "+f"(acc[i][j]) :: "memory");
        PROFC(9 + 2 * i);
        asm volatile("bar.sync %0, 128;" :: "r"(bar) : "memory");
        if (!i && R8A < 8) wgmma_fence();
#pragma unroll
        for (int j = 0; j < 8; j++) {
            const float* a = acc[i] + 8 * j;
            if (!i && j + R8A < 8) wgmma_n16<1>(acc[1] + 8 * (j + R8A), da + 64 * (8 + j + R8A), dg);
            stsm_x4_t(sa[j & 3] + (2 * i + (j >> 2)) * 4096, pack2(a[0], a[1]), pack2(a[2], a[3]), pack2(a[4], a[5]), pack2(a[6], a[7]));
            if ((P_R8F || P_R8I) && (j & 1) && j < 7 && (i || j + R8A >= 7)) pause(inv ? P_R8I : P_R8F);
        }
        if (!i && R8A < 8) wgmma_commit();
        PROFC(10 + 2 * i);
        if (i ? inv || !(FPOS & 1) : inv && HF) fence_proxy_async_smem();
        __syncwarp();
        if (inv) warp_arrive(sb + OFF_BAR + 8 * BAR_VW);
    }
}

template<int N> DEVI void c_take(float (&acc)[32], uint32_t (&p)[16]) {
    wgmma_wait<N>();
#pragma unroll
    for (int i = 0; i < 32; i++) asm volatile("" : "+f"(acc[i]) :: "memory");
#pragma unroll
    for (int i = 0; i < 16; i++) p[i] = pack2(acc[2 * i], acc[2 * i + 1]);
}
DEVI uint64_t desc_at(uint64_t d, uint32_t o) { return (d & 0xffffffff00000000ull) | ((uint32_t)d + o); }
DEVI void c_cols(float (&acc)[32], uint64_t df, uint64_t db, int o) {
    wgmma_fence();
    wgmma_ss_n64<0>(acc, df, desc_at(db, o));
#pragma unroll
    for (int s = 1; s < 4; s++) wgmma_ss_n64<1>(acc, df + 2 * s, desc_at(db, o + 256 * s));
    wgmma_commit();
}

DEVI void phase_c(uint32_t sb, int ps, bool rot, int w, int lane) {
    const int warp = ps, bar = 5 + ps;
    PROFC(0);
    const uint32_t rb = sb + OFF_U + ps * 16384;
    const uint64_t df = make_desc(OFF_F, 16, 1024), db = make_desc(OFF_U + ps * 16384, 16, 1024);
    float acc[2][32];
    c_cols(acc[0], df, db, 0);
    c_cols(acc[1], df, db, 128);
    sched_fence();
    asm volatile("" : "+r"(lane));
    const int g = lane & 7, l3 = (lane >> 3) & 1, l4 = lane >> 4;
    uint32_t wf[2][4][4];
    const uint32_t wo = sb + OFF_W + (1 - ps) * 18432 + l4 * 9216 + g * 64 + ((w ^ (g >> 1)) << 4);
    uint32_t wd = wo + l3 * 1152, wm[2] = {wo + 4608 + (((rot ? 4 : 3) - l3) & 3) * 1152, wo + 4608 + ((rot ? 2 : 1) - l3) * 1152};
    uint32_t xa = rb + w * 4096 + l4 * 1024 + g * 128 + (((4 * l3) ^ g) << 4);
    uint32_t oa = rb + (4 * w + (g >> 1)) * 1024 + (1 - l3) * 512 + (((4 * (g & 1) + l4) ^ (4 - 4 * l3) ^ (g >> 1)) << 4);
    auto load_w = [&](int h) {
#pragma unroll
        for (int j = 0; j < 4; j++) ldsm_x4_t(wf[h][j], (j < 2 ? wd + h * 2304 : wm[h]) + (j & 1) * 512);
    };
    uint32_t tw[8][3];
    {
        const float a0 = (float)(8 * w + (lane >> 2)) * 0.0061359231515425649f, q2 = (float)(2 * (lane & 3)), p16 = (float)(16 * ps);
        const float b0 = a0 * (q2 + p16), b1 = a0 * (q2 - p16);
#pragma unroll
        for (int j = 0; j < 4; j++) {
            const float u = fmaf(a0, 8.f * j, j < 2 ? b0 : b1), v = u + a0, su = __sinf(u), sv = __sinf(v);
            tw[j][0] = pack2(__cosf(u), __cosf(v)); tw[j][1] = pack2(-su, -sv); tw[j][2] = pack2(su, sv);
        }
    }
#pragma unroll
    for (int j = 0; j < 4; j++) asm volatile("" : "+r"(tw[j][0]), "+r"(tw[j][1]), "+r"(tw[j][2]));
    asm volatile("" : "+r"(wd), "+r"(wm[0]), "+r"(wm[1]), "+r"(xa), "+r"(oa));
    sched_fence();
    auto twiddle = [&](uint32_t& x, uint32_t& y, int j) { cmul2(x, y, tw[j][0], tw[j][1], tw[j][2]); };
#pragma unroll
    for (int h = 0; h < 2; h++) {
        uint32_t p[16], a[4][4];
        c_take<1>(acc[h], p);
        if (h == 0) PROFC(1);
#pragma unroll
        for (int i = 0; i < 8; i++) {
            twiddle(p[2 * i], p[2 * i + 1], (i & 3) ^ h);
            a[(i & 3) ^ h][i >> 2] = p[2 * i];
            a[(i & 3) ^ h][2 + (i >> 2)] = p[2 * i + 1];
        }
        wgmma_fence();
        wgmma_rs_n64<0>(acc[h], a[0], desc_at(df, 4 * ps));
        wgmma_rs_n64<1>(acc[h], a[1], desc_at(df, 4 * ps + 2));
        wgmma_rs_n64<1>(acc[h], a[2], desc_at(df, 4 - 4 * ps));
        wgmma_rs_n64<1>(acc[h], a[3], desc_at(df, 6 - 4 * ps));
        wgmma_commit();
        load_w(h);
    }
    PROFC(2);
#pragma unroll
    for (int h = 0; h < 2; h++) {
        uint32_t p[16], a[4][4];
        c_take<1>(acc[h], p);
#pragma unroll
        for (int i = 0; i < 8; i++) {
            const int j = i >> 1, r = i & 1;
            if (j < 2) cmul2(p[4 * j + r], p[4 * j + 2 + r], wf[h][j][r], wf[h][j][2 + r]);
            else cmul2c(p[4 * j + r], p[4 * j + 2 + r], wf[h][j][r], wf[h][j][2 + r]);
            a[j][r] = p[4 * j + 2 + r];
            a[j][2 + r] = p[4 * j + r];
        }
        wgmma_fence();
        wgmma_rs_n64<0>(acc[h], a[0], df);
#pragma unroll
        for (int j = 1; j < 4; j++) wgmma_rs_n64<1>(acc[h], a[j], df + 2 * j);
        wgmma_commit();
    }
    PROFC(3);
#pragma unroll
    for (int j = 0; j < 12; j++) tw[4 + j / 3][j % 3] = ps ? tw[(j / 3) ^ 2][j % 3] : tw[j / 3][j % 3];
    uint32_t p[16];
    auto put = [&](int h) {
#pragma unroll
        for (int i = 0; i < 8; i++) twiddle(p[4 * (i >> 1) + (i & 1)], p[4 * (i >> 1) + 2 + (i & 1)], 4 + (i >> 1));
        if (!h) {
#pragma unroll
            for (int i = 0; i < 16; i++) asm volatile("" : "+r"(p[i]) :: "memory");
            asm volatile("bar.sync %0, 128;" :: "r"(bar) : "memory");
        }
#pragma unroll
        for (int j = 0; j < 4; j++) stsm_x4((xa ^ (j << 4)) + h * 2048, p[4 * j], p[4 * j + 1], p[4 * j + 2], p[4 * j + 3]);
        if (h && ps && !(FPOS & 2)) fence_proxy_async_smem();
    };
    c_take<1>(acc[0], p);
    put(0);
    c_take<0>(acc[1], p);
    if (!ps) put(1);
    else {
        float fin[2][64];
        auto cols = [&](int n) {
            wgmma_fence();
            wgmma_n128_set(fin[n], df, make_desc(OFF_U + n * 16384, 2048, 1024));
#pragma unroll
            for (int s = 1; s < 4; s++) wgmma_n128<0, 1>(fin[n], df + 2 * s, make_desc(OFF_U + n * 16384, 2048, 1024) + 256 * s, 1);
            wgmma_commit();
            sched_fence();
        };
        cols(0);
#pragma unroll
        for (int i = 0; i < 16; i++) asm volatile("" : "+r"(p[i]) :: "memory");
        put(1);
        PROFC(4);
#pragma unroll
        for (int n = 0; n < 2; n++) {
            wgmma_wait_all(fin[n]);
            asm volatile("bar.sync 6, 128;" ::: "memory");
            if (!n && (FPOS & 2)) fence_proxy_async_smem();
            if (!n) cols(1);
#pragma unroll
            for (int i = 0; i < 8; i++) {
                const int r = i >> 1;
                const float* a = fin[n] + 8 * i;
                stsm_x4((oa ^ ((r ^ (2 * (i & 1))) << 4)) + r * 128 + (n - 1) * 16384, pack2(a[0], a[1]), pack2(a[2], a[3]), pack2(a[4], a[5]), pack2(a[6], a[7]));
                if (P_CF && (i & 1) && i < 7) pause(P_CF);
            }
        }
        if (!(FPOS & 4)) fence_proxy_async_smem();
        asm volatile("bar.sync 6, 128;" ::: "memory");
        if (FPOS & 4) fence_proxy_async_smem();
    }
    PROFC(5);
}

#define P_T 80
#define P_C 300
#define PACE_HA 100
#define PACE_HB 0
#define HN 4
#define PACE_V 100
#define VFIRST 4
#define K_XE 60
#define PACE_H 200
#define T_W0 2000
#define T_XS 2000
#define D_XS 0
#define P_XS 500
#define T_G 0
#define T_BA 400
#define T_W1 3000
#define P_W 0
#define P_XE 600
#define P_R0 0
#define P_CAR 300
#define HWZ 2
#define R_REL 1
#define R_MID 4
#define W_EARLY 0
#define SEP 0
#define UN 1
#define FA0 16
#define P_CARB 200
#define D_CAR 20
#define HPOLL 1
#define P_HP 0
#define PF0 0
#define NPF 1
#define PFM 63
#define PFT 0
#define T_PFT 0
#define N_T 1
#define HS0 3
#define T_B2 4000
#define T_W 4500
#define PACE_U 200
#define PACE_L 0
#define T_FA 0
#define REG_M 216
#define REG_H 72
#define NS 4
#define QM1 42
#define QM2 36
#define SLOT_OF(k) (((k) + 1) % 4)
DEVI void tma_prefetch_4d(const CUtensorMap* map, int c0, int c1, int c2, int c3) {
    asm volatile("cp.async.bulk.prefetch.tensor.4d.L2.global [%0, {%1, %2, %3, %4}];" :: "l"(map), "r"(c0), "r"(c1), "r"(c2), "r"(c3) : "memory");
}
DEVI void bar_sync(int id, int n) { asm volatile("bar.sync %0, %1;" :: "r"(id), "r"(n) : "memory"); }
DEVI void bar_arrive(int id, int n) { asm volatile("bar.arrive %0, %1;" :: "r"(id), "r"(n) : "memory"); }
DEVI uint4 ldg128(const void* p) { uint4 v; asm volatile("ld.global.nc.v4.u32 {%0, %1, %2, %3}, [%4];" : "=r"(v.x), "=r"(v.y), "=r"(v.z), "=r"(v.w) : "l"(p)); return v; }
DEVI uint32_t ldg16(const void* p) { uint32_t v; asm volatile("ld.global.nc.u16 %0, [%1];" : "=r"(v) : "l"(p)); return v; }
DEVI uint32_t bf_fma2(uint32_t a, uint32_t b, uint32_t c) { uint32_t d; asm("fma.rn.bf16x2 %0, %1, %2, %3;" : "=r"(d) : "r"(a), "r"(b), "r"(c)); return d; }
DEVI uint32_t lo2(uint32_t a) { uint32_t d; asm("{\n.reg .b16 l, h;\nmov.b32 {l, h}, %1;\nmov.b32 %0, {l, l};\n}" : "=r"(d) : "r"(a)); return d; }
DEVI uint32_t hi2(uint32_t a) { uint32_t d; asm("{\n.reg .b16 l, h;\nmov.b32 {l, h}, %1;\nmov.b32 %0, {h, h};\n}" : "=r"(d) : "r"(a)); return d; }
DEVI void bulk_wait_read() { asm volatile("cp.async.bulk.wait_group.read 0;" ::: "memory"); }

DEVI float lds32f(uint32_t a) { float v; asm volatile("ld.shared.f32 %0, [%1];" : "=f"(v) : "r"(a) : "memory"); return v; }
DEVI uint32_t mbar_test(uint32_t bar, uint32_t parity) {
    uint32_t ok;
    asm volatile("{\n.reg .pred p;\nmbarrier.test_wait.parity.shared::cta.b64 p, [%1], %2;\nselp.u32 %0, 1, 0, p;\n}" : "=r"(ok) : "r"(bar), "r"(parity) : "memory");
    return ok;
}
template<int TA> DEVI void ring_steps(float (&acc)[2][64], uint32_t sb, uint32_t fb, int n, int ns, int s, uint32_t ph, int first_bar, int last_bar, int pi) {
    const uint64_t da0 = TA ? make_desc(0, 2048, 256, 3) : make_desc(0, 16, 1024), db0 = make_desc(16384, 16, 1024);
    const uint32_t fe = fb + 8 * ns, de = sb + OFF_BAR + 8 * BAR_EMPTY - fb;
    uint32_t eb = sb + OFF_BAR + 8 * BAR_HR, f = fb + 8 * s;
    uint64_t da = da0 + (uint32_t)(s * 2048), db = db0 + (uint32_t)(s * 2048);
    bool first = true;
    if (TA) PROFT(72);
    mbar_wait(f, ph);
    if (TA) PROFT(73);
    if (first_bar) bar_sync(first_bar, 256);
    if (TA) PROFT(74);
#pragma unroll 1
    for (;;) {
        PROFK(pi++);
        wgmma_fence();
        constexpr int QM = TA ? QM2 : QM1;
#pragma unroll
        for (int j = 0; j < 8; j++) {
            wgmma_n128<TA, 0>(acc[j & 1], da + 512 * (j & 1) + (TA ? 32 : 2) * (j >> 1), db + 2 * (j >> 1), j > 1 || !first);
            if ((QM >> j) & 1) {
                wgmma_commit();
                wgmma_wait<1>();
                if (!(QM & ((1 << j) - 1))) warp_arrive(eb);
                wgmma_fence();
            }
        }
        wgmma_commit();
        first = false;
        --n;
        if (TA && n == 0) break;
        eb = f + de;
        f += 8; da += 2048; db += 2048;
        if (f == fe) { f = fb; da = da0; db = db0; ph ^= 1; }
        const uint32_t ok = mbar_test(f, ph);
        wgmma_wait<1>();
        if (!ok) mbar_wait(f, ph);
        __syncwarp();
        if (!TA && n == 1) break;
    }
    if (!TA) {
        PROFK(pi++);
        wgmma_fence();
#pragma unroll
        for (int j = 0; j < 8; j++) {
            wgmma_n128<TA, 0>(acc[j >> 2], da + 512 * (j >> 2) + 2 * (j & 3), db + 2 * (j & 3), 1);
            if (j == 3) {
                wgmma_commit();
                wgmma_wait<1>();
                warp_arrive(eb);
                wgmma_fence();
            }
        }
        wgmma_commit();
    }
    if (last_bar) bar_arrive(last_bar, 256);
}

__global__ void __cluster_dims__(2, 1, 1) __launch_bounds__(384, 1)
fused_kernel(const __grid_constant__ CUtensorMap mapB, const __grid_constant__ CUtensorMap mapX,
             const __grid_constant__ CUtensorMap mapXs, const __grid_constant__ CUtensorMap mapU0,
             const __grid_constant__ CUtensorMap mapU2, const __grid_constant__ CUtensorMap mapXe,
             const __grid_constant__ CUtensorMap mapCre, const __grid_constant__ CUtensorMap mapCim,
             const __grid_constant__ CUtensorMap mapV, const __grid_constant__ CUtensorMap mapO,
             const __grid_constant__ CUtensorMap mapWr, const __grid_constant__ CUtensorMap mapWi,
             const __grid_constant__ CUtensorMap mapH,
             const __grid_constant__ Params P) {
    extern __shared__ __align__(1024) uint8_t sm[];
    const uint32_t sb = smem_u32(sm);
    const uint32_t bars = sb + OFF_BAR;
    const unsigned cl = blockIdx.x >> 1;
    const unsigned c7 = ((cl - 36) * 37 >> 8) & 7, r7 = cl - 37 - 7 * c7;
    const unsigned ra = 32 + 8 * cl, rb_ = ((cl - 4) & 24) + ((cl - 5) & 7), rc = 33 + 8 * c7 + min(r7, 6u);
    int role;
    asm("{\n.reg .pred p;\nsetp.lt.u32 p, %1, 64;\nselp.u32 %0, %4, %1, p;\nsetp.lt.u32 p, %1, 36;\nselp.u32 %0, %3, %0, p;\n"
        "setp.lt.u32 p, %1, 4;\nselp.u32 %0, %2, %0, p;\n}" : "=r"(role) : "r"(cl), "r"(ra), "r"(rb_), "r"(rc));
    const int b = role * 2 + (blockIdx.x & 1), tid = threadIdx.x, warp = __shfl_sync(0xffffffffu, tid >> 5, 0), lane = tid & 31;
    const bool main_cta = b < 128;
    if (b == 129) return;
    const int rp = (b >> 1) & 3, mq = ((b >> 3) & 2) + (b & 1), dt = ((b >> 1) & 4) + (b >> 5), tc = 4 * rp + mq;
    if (warp == 8 && elect()) {
        PROF(0);
#pragma unroll
        for (int i = 0; i < 5; i++) mbar_init(bars + 8 * i, 1);
        fence_barrier_init();
        fence_proxy_async_smem();
        PROFX(88);
    }
    if (warp >= 8) {
        __syncwarp();
        reg_dealloc<REG_H>();
        if (warp == 8) bar_arrive(0, 384);
    }
    if (warp == 8 && elect()) {
        if (main_cta) {
#pragma unroll 1
            for (int k = 0; k < 5; k++) {
                const uint32_t full = bars + 8 * (BAR_FULL + k), st = sb + k * SLOT;
                mbar_expect_tx(full, SLOT);
                tma_load_4d(st, &mapB, full, k * 64, 0, 0, dt * 8);
                tma_load_4d(st + 16384, &mapX, full, k * 64, 0, 0, tc * 64);
                if (k == 0) PROFX(89);
            }
        }
        PROF(27);
    }
    const int cls = b == 128 ? 128 : (b & 31) ? (b & 31) + 64 * (b >> 5) : (b == 64 ? 32 : b == 32 ? 64 : b);
    if (warp != 8 && elect()) {
        if (warp == 11) PROFG(0);
        const int u = warp - (warp > 8);
        if ((sb & 0x3FFFF) != SB0) __trap();
        mbar_init(bars + 8 * (5 + u), 1);
        if (!u) mbar_arrive(bars + 8 * (BAR_FULL + 5));
        if (u == 8) sts32(sb + OFF_KEPT + 32, 0);
        mbar_init(bars + 8 * (16 + u), u ? 4 : 1);
        mbar_init(bars + 8 * (27 + u), u < 1 ? 4 : u == 6 ? 8 : (u == 7 || u == 8) ? 64 : 1);
        fence_barrier_init();
        fence_proxy_async_smem();
    }
    __syncwarp();
    const bool real_cls = (cls & 127) == 0;
    const int t = tid & 127;
    auto load_epoch = [&]() {
        unsigned e;
        asm volatile("ld.relaxed.gpu.global.u32 %0, [%1];" : "=r"(e) : "l"(&g_cnt[CNT_EPOCH * CS]));
        return e + 1;
    };
    const int g = lane >> 2, q = lane & 3;

    if (warp < 8) {
        reg_alloc<REG_M>();
        const int wg = warp >> 2, w = warp & 3;
        if (tid == 0) PROFX(94);
        bar_sync(0, 384);
        if (tid == 224) PROFG(8);
        auto kept = [&](int i) { uint64_t v; asm volatile("ld.volatile.shared.u64 %0, [%1];" : "=l"(v) : "r"(sb + OFF_KEPT + 8 * i) : "memory"); return v; };
        const uint32_t fb = bars + 8 * (BAR_FULL + 5 * wg);
        if (wg) {
            uint32_t fa[16][4];
            auto load_fa = [&](int i0, int i1) {
#pragma unroll
                for (int i = i0; i < i1; i++)
                    asm volatile("ld.global.nc.L1::no_allocate.v4.u32 {%0, %1, %2, %3}, [%4];" : "=r"(fa[i][0]), "=r"(fa[i][1]), "=r"(fa[i][2]), "=r"(fa[i][3]) : "l"((const uint4*)c_tab + i * 128 + t));
            };
            {
                const int pp = (dt * 64 + 8 * (t & 64) + (t & 63)) & 1023;
                const uint32_t lr_ = ldg16(P.lam_re + pp), li_ = ldg16(P.lam_im + pp), ld_ = ldg16(P.log_dt + pp);
                const unsigned epoch = load_epoch();
                if (T_FA) pause(T_FA);
                load_fa(0, FA0);
                if (t < 64 && main_cta) g_agg[rp * 2048 + (dt + (t >> 5) * 8) * 128 + lane * 4 + mq] = make_uint4(0u, 0u, 0u, 0u);
                if (t < 4) asm volatile("st.shared.u64 [%0], %1;" :: "r"(sb + OFF_KEPT + 8 * lane),
                    "l"(lane == 0 ? (P.swapB ? 0xffffffffull : 0xffffff7full) | ((uint64_t)epoch << 32) : lane == 1 ? (uint64_t)g_agg : (uint64_t)&mapB) : "memory");
                const float lr = bf_lo(lr_), li = bf_lo(li_);
                const float dl = bf_round(expf(bf_lo(ld_)));
                const float mag = expf(dl * lr);
                float sn, cs; sincospif(dl * li * 0.31830988618379067f, &sn, &cs);
                const float2 l1 = make_float2(mag * cs, mag * sn);
                const float inv = 1.f / (lr * lr + li * li);
                const float2 cf = cmul(make_float2(l1.x - 1.f, l1.y), make_float2(lr * inv, -li * inv));
                sts128u(sb + OFF_K + 16 * t, __float_as_uint(l1.x), __float_as_uint(P.swapB ? -l1.y : l1.y),
                        P.swapB ? pack2(-cf.y, cf.x) : pack2(cf.x, -cf.y), P.swapB ? pack2(-cf.x, -cf.y) : pack2(-cf.y, -cf.x));
                if (tid == 128) PROFX(92);
            }
            {
                const int kk = (t >> 3) & 7, r = t & 7;
                float sn, cs;
                sincospif((float)(((cls + 256 * kk) * r) & 2047) * (1.f / 1024.f), &sn, &cs);
                sn *= 1.f / 1024.f; cs *= 1.f / 1024.f;
                const uint32_t gf = sb + OFF_G + kk * 16 + r * 2, gi = sb + OFF_G + 512 + r * 16 + (kk & 1) * 128 + (kk & 6);
                if (t < 64) {
                    sts16(gf, cs); sts16(gf + 128, real_cls ? 0.f : sn); sts16(gf + 256, -sn); sts16(gf + 384, real_cls ? 0.f : cs);
                    sts16(gi, cs); sts16(gi + 8, -sn); sts16(gi + 256, sn); sts16(gi + 264, cs);
                }
            }
            if (main_cta) {
                load_fa(FA0, 16);
                if (t == 0) PROFX(91);
                const uint32_t ua = sb + OFF_U + (lane >> 4) * 4096 + (8 * w + (lane & 7)) * 128 + ((((lane >> 3) & 1) ^ (lane & 7)) << 4);
                float acc[4][32];
                const uint64_t db = make_desc(OFF_U, 8192, 1024);
                uint32_t x[4][8], y[4][8];
                float gp[4][4];
#pragma unroll
                for (int m = 0; m < 6; m++) {
                    if (m >= 2) {
                        const int n = m - 2;
                        if (m < 5) wgmma_wait<1>(); else wgmma_wait<0>();
#pragma unroll
                        for (int i = 0; i < 32; i++) asm volatile("" : "+f"(acc[n][i]) :: "memory");
                        asm volatile("" : "+f"(gp[n][0]), "+f"(gp[n][2]) :: "memory");
#pragma unroll
                        for (int j = 0; j < 8; j++) { x[n][j] = pack2(acc[n][4 * j], acc[n][4 * j + 1]); y[n][j] = pack2(acc[n][4 * j + 2], acc[n][4 * j + 3]); }
                    }
                    if (m < 4) {
                        mbar_wait(bars + 8 * (BAR_XC + m), 0);
                        if (t == 0 && m == 3) PROF(8);
                        wgmma_fence();
                        wgmma_rs_n64<0, 1>(acc[m], fa[4 * m], db + 512 * m);
#pragma unroll
                        for (int j = 1; j < 4; j++) wgmma_rs_n64<1, 1>(acc[m], fa[4 * m + j], db + 512 * m + 128 * j);
#pragma unroll
                        for (int j = 0; j < 4; j++) wgmma_n8(gp[m], make_desc(OFF_U, 16, 1024) + 512 * m + 2 * j, make_desc(OFF_GW, 16, 1024) + 2 * j, j);
                        wgmma_commit();
                    }
                }
                if (t < 4) {
#pragma unroll
                    for (int j = 0; j < 8; j++) {
                        const uint32_t s0 = bf_add2(x[0][j], x[2][j]), s2 = bf_add2(x[1][j], x[3][j]), ty = bf_sub2(y[1][j], y[3][j]), sy = bf_add2(y[1][j], y[3][j]);
                        const uint32_t b0 = y[0][j], b2 = y[2][j];
                        y[1][j] = bf_sub2(x[3][j], x[1][j]); x[1][j] = bf_sub2(x[0][j], x[2][j]);
                        x[0][j] = bf_add2(s0, s2); y[0][j] = bf_sub2(s0, s2);
                        x[2][j] = bf_add2(b0, ty); y[2][j] = bf_add2(sy, b2) ^ 0x80008000u;
                        x[3][j] = bf_sub2(b0, ty); y[3][j] = bf_sub2(b2, sy);
                    }
                } else {
#pragma unroll
                    for (int j = 0; j < 8; j++) {
                        const uint32_t s0x = bf_add2(x[0][j], x[2][j]), s1x = bf_sub2(x[0][j], x[2][j]), s2x = bf_add2(x[1][j], x[3][j]), tx = bf_sub2(x[1][j], x[3][j]);
                        const uint32_t s0y = bf_add2(y[0][j], y[2][j]), s1y = bf_sub2(y[0][j], y[2][j]), s2y = bf_add2(y[1][j], y[3][j]), ty = bf_sub2(y[1][j], y[3][j]);
                        x[0][j] = bf_add2(s0x, s2x); y[0][j] = bf_add2(s0y, s2y);
                        x[1][j] = bf_add2(s1x, ty); y[1][j] = bf_sub2(s1y, tx);
                        x[2][j] = bf_sub2(s0x, s2x); y[2][j] = bf_sub2(s0y, s2y);
                        x[3][j] = bf_sub2(s1x, ty); y[3][j] = bf_add2(s1y, tx);
                    }
                }
                helper_sync();
                if (q == 0) {
#pragma unroll
                    for (int i = 0; i < 2; i++)
                        sts128u(sb + OFF_GW + (16 * w + 8 * i + g) * 16, __float_as_uint(gp[0][2 * i]), __float_as_uint(gp[1][2 * i]), __float_as_uint(gp[2][2 * i]), __float_as_uint(gp[3][2 * i]));
                }
#pragma unroll
                for (int c = 0; c < 4; c++)
#pragma unroll
                    for (int j = 0; j < 8; j += 2) {
                        stsm_x4((ua ^ (j << 4)) + c * 8192, x[c][j], x[c][j + 1], y[c][j], y[c][j + 1]);
                        if (P_S1 && (j & 2)) pause(P_S1);
                    }
                if (t == 0) PROF(21);
            }
            __syncwarp();
            warp_arrive(bars + 8 * BAR_S1);
        }
        {
            float acc[2][64];
            float2 lam8[2], lam32[2], lam64[2], l32q[2], ex[2];
            float2 ag[2][4];
            if (main_cta) {
                ring_steps<0>(acc, sb, fb, 16, 5 - wg, wg * SLOT_OF(16), 0, 2 * wg, 2 + wg, 16 * wg);
                mbar_wait(bars + 8 * BAR_S1, 0);
                const uint4* ap = (const uint4*)kept(1) + (((tc - 1 - q) >> 2) * 2048 + (dt + 8 * wg) * 128 + t);
                const uint64_t k0 = kept(0);
                const uint32_t fl = (uint32_t)k0;
                uint32_t tag = ((uint32_t)(k0 >> 32) & 7) | 8;
                float2 lam1[2], la[2], lb[2], l2[2], l4[2], wq[2], w4[2];
                uint32_t m0[2], m1[2], kr[8], ki[8];
                auto weights = [&](int i) {
                    const float2 l128 = csq(lam64[i]), l256 = csq(l128), one = make_float2(1.f, 0.f);
                    w4[i] = csq(l256);
                    wq[i] = cmul(((tc - 1 - q) & 1) ? l128 : one, ((tc - 1 - q) & 2) ? l256 : one);
                    l32q[i] = cmul((q & 1) ? la[i] : one, (q & 2) ? lb[i] : one);
                    asm volatile("" : "+f"(w4[i].x), "+f"(w4[i].y), "+f"(wq[i].x), "+f"(wq[i].y), "+f"(l32q[i].x), "+f"(l32q[i].y));
                };
#pragma unroll
                for (int i = 0; i < 2; i++) {
                    const uint4 kv = lds128u(sb + OFF_K + (64 * wg + 32 * i + (t >> 2)) * 16);
                    lam1[i] = make_float2(__uint_as_float(kv.x), __uint_as_float(kv.y));
                    m0[i] = kv.z; m1[i] = kv.w;
                    l2[i] = csq(lam1[i]); l4[i] = csq(l2[i]); lam8[i] = csq(l4[i]);
                    lam32[i] = csq(csq(lam8[i])); lam64[i] = csq(lam32[i]);
                    la[i] = q >= 1 ? lam32[i] : make_float2(0.f, 0.f); lb[i] = q >= 2 ? lam64[i] : make_float2(0.f, 0.f);
                    asm volatile("" : "+f"(lam8[i].x), "+f"(lam8[i].y), "+f"(la[i].x), "+f"(la[i].y), "+f"(lb[i].x), "+f"(lb[i].y), "+f"(lam64[i].x), "+f"(lam64[i].y));
                    if (W_EARLY) weights(i);
                }
                kr[1] = pack2(l2[0].x, l2[1].x); ki[1] = pack2(l2[0].y, l2[1].y); kr[3] = pack2(l4[0].x, l4[1].x); ki[3] = pack2(l4[0].y, l4[1].y);
                asm volatile("" : "+r"(kr[1]), "+r"(ki[1]), "+r"(kr[3]), "+r"(ki[3]));
                uint32_t pub = q == 3 && tc < 15;
                const uint4* as = ap + (2045 + mq);
                asm volatile("" : "+l"(ap), "+l"(as), "+r"(tag), "+r"(pub));
                sched_fence();
                float2 v[2];
                wgmma_wait<1>();
#pragma unroll
                for (int o = 0; o < 64; o++) asm volatile("" : "+f"(acc[0][o]) :: "memory");
#pragma unroll
                for (int i = 0; i < 2; i++) {
#pragma unroll
                    for (int r = 1; r < 8; r++) {
#pragma unroll
                        for (int c = 0; c < 4; c++) {
                            const int o = 16 * c + 4 * (r >> 1) + (r & 1), u = 16 * c + 4 * ((r - 1) >> 1) + ((r - 1) & 1);
                            const float2 n = cfma(lam1[i], make_float2(acc[i][u], acc[i][u + 2]), make_float2(acc[i][o], acc[i][o + 2]));
                            acc[i][o] = n.x; acc[i][o + 2] = n.y;
                        }
                        if (!i && r == R_REL) {
#pragma unroll
                            for (int o = 0; o < 64; o++) asm volatile("" : "+f"(acc[0][o]));
                            sched_fence();
                            wgmma_wait_all(acc[1]);
                            warp_arrive(bars + 8 * (BAR_EMPTY + SLOT_OF(15)));
                            sched_fence();
                            if (tid == 0) PROF(3);
                            if (tid == 128) PROF(25);
                            if (tid == 224) PROFG(12);
                        }
                        if (i && r == R_MID) {
#pragma unroll
                            for (int o = 0; o < 64; o++) asm volatile("" : "+f"(acc[1][o]));
                            asm volatile("" : "+f"(v[0].x), "+f"(v[0].y));
                            sched_fence();
                        }
                    }
#pragma unroll
                    for (int c = 0; c < 4; c++) ag[i][c] = make_float2(acc[i][16 * c + 13], acc[i][16 * c + 15]);
                    v[i] = ag[i][0];
#pragma unroll
                    for (int c = 1; c < 4; c++) v[i] = cfma(lam8[i], v[i], ag[i][c]);
                    float2 n = make_float2(__shfl_up_sync(0xffffffffu, v[i].x, 1, 4), __shfl_up_sync(0xffffffffu, v[i].y, 1, 4));
                    v[i] = cfma(la[i], n, v[i]);
                    n = make_float2(__shfl_up_sync(0xffffffffu, v[i].x, 2, 4), __shfl_up_sync(0xffffffffu, v[i].y, 2, 4));
                    v[i] = cfma(lb[i], n, v[i]);
                }
                asm volatile("{\n.reg .b64 a, b;\n.reg .pred p;\nsetp.ne.u32 p, %5, 0;\nmov.b64 a, {%1, %2};\nmov.b64 b, {%3, %4};\n@p st.relaxed.gpu.global.v2.b64 [%0], {a, b};\n}"
                    :: "l"(as), "r"((__float_as_uint(v[0].x) & ~15u) | tag), "r"(__float_as_uint(v[0].y)),
                       "r"((__float_as_uint(v[1].x) & ~15u) | tag), "r"(__float_as_uint(v[1].y)), "r"(pub) : "memory");
                PROFS(72 + 8 * wg);
                sched_fence();
                uint4 rr[4];
                auto poll = [&]() {
#pragma unroll
                    for (int n = 0; n < 4; n++)
                        asm volatile("{\n.reg .b64 a, b;\n.reg .pred p;\nsetp.lt.s32 p, %5, %6;\ncvt.u64.u32 a, %7;\nmov.b64 b, a;\n"
                                     "@p ld.relaxed.gpu.global.v2.b64 {a, b}, [%4];\nmov.b64 {%0, %1}, a;\nmov.b64 {%2, %3}, b;\n}"
                            : "=r"(rr[n].x), "=r"(rr[n].y), "=r"(rr[n].z), "=r"(rr[n].w) : "l"(ap - 2048 * n), "r"(4 * n), "r"(tc - q), "r"(tag) : "memory");
                };
                uint32_t hp[2][32];
                auto scale = [&](int i, uint32_t& x, uint32_t& y) {
                    const uint32_t u = bf_fma2(lo2(m0[i]), x, bf_mul2(hi2(m0[i]), y));
                    y = bf_fma2(lo2(m1[i]), x, bf_mul2(hi2(m1[i]), y)); x = u;
                };
#pragma unroll
                for (int i = 0; i < 2; i++) {
                    ex[i] = make_float2(__shfl_up_sync(0xffffffffu, v[i].x, 1, 4), __shfl_up_sync(0xffffffffu, v[i].y, 1, 4));
#pragma unroll
                    for (int j = 0; j < 16; j++) {
                        const int o = 4 * (j >> 2) + 16 * (j & 1) + ((j >> 1) & 1), u = 8 * (j >> 2) + (j & 3);
                        hp[i][u] = pack2(acc[i][o], acc[i][o + 32]); hp[i][u + 4] = pack2(acc[i][o + 2], acc[i][o + 34]);
                    }
                    if (q == 0) ex[i] = make_float2(0.f, 0.f);
                }
                if (SEP) {
#pragma unroll
                    for (int j = 0; j < 64; j++) asm volatile("" : "+r"(hp[j >> 5][j & 31]));
                    sched_fence();
                }
#pragma unroll
                for (int j = 0; j < 32; j++) scale(j >> 4, hp[j >> 4][2 * (j & 12) + (j & 3)], hp[j >> 4][2 * (j & 12) + (j & 3) + 4]);
#pragma unroll
                for (int i = 0; i < 2; i++) {
#pragma unroll
                    for (int j = 0; j < 32; j++) asm volatile("" : "+r"(hp[i][j]));
                    asm volatile("" : "+f"(ex[i].x), "+f"(ex[i].y));
                }
                PROFS(73 + 8 * wg);
                mbar_wait(bars + 8 * (wg ? BAR_HD : BAR_EMPTY + 4), 0);
                if (wg) mbar_wait(bars + 8 * BAR_WR, 0);
                pause((wg ? P_CARB : P_CAR) + D_CAR * tc);
                poll();
                sched_fence();
                uint32_t hs = sb + OFF_HS + (lane >> 4) * 1024 + w * 256 + (lane & 7) * 32 + (((lane << 1) ^ (lane << 2)) & 16), hs1 = hs + 16384 + wg * 18432;
                asm volatile("" : "+r"(hs), "+r"(hs1));
                {
                    const uint32_t cj = (fl & 128) ? 0u : 0x80008000u;
                    kr[0] = pack2(lam1[0].x, lam1[1].x); ki[0] = pack2(lam1[0].y, lam1[1].y) ^ cj; kr[7] = pack2(lam8[0].x, lam8[1].x); ki[7] = pack2(lam8[0].y, lam8[1].y) ^ cj;
                    ki[1] ^= cj; ki[3] ^= cj;
                    kr[2] = kr[1]; ki[2] = ki[1]; cmul2(kr[2], ki[2], kr[0], ki[0]);
                    const uint32_t n4 = neg2(ki[3]);
#pragma unroll
                    for (int j = 0; j < 3; j++) { kr[4 + j] = kr[j]; ki[4 + j] = ki[j]; cmul2(kr[4 + j], ki[4 + j], kr[3], ki[3], n4); }
#pragma unroll
                    for (int j = 0; j < 8; j++) asm volatile("" : "+r"(kr[j]), "+r"(ki[j]));
                    if (!W_EARLY) { weights(0); weights(1); }
                }
                sched_fence();
                float2 pt[2];
                auto sum = [&]() {
                    uint32_t bad = 0;
#pragma unroll
                    for (int j = 0; j < 4; j++) bad |= (rr[j].x ^ tag) | (rr[j].z ^ tag);
#pragma unroll
                    for (int i = 0; i < 2; i++) {
                        auto val = [&](int n) { return make_float2(__uint_as_float(i ? rr[n].z : rr[n].x), __uint_as_float(i ? rr[n].w : rr[n].y)); };
                        pt[i] = cmul(wq[i], cfma(w4[i], cfma(w4[i], cfma(w4[i], val(3), val(2)), val(1)), val(0)));
                        asm volatile("" : "+f"(pt[i].x), "+f"(pt[i].y));
                    }
                    return __any_sync(0xffffffffu, bad & 15);
                };
                if (sum()) {
#pragma unroll 1
                    for (unsigned n = 0; n < SPIN_LIMIT; n++) {
                        if (n < 3) PROFS(74 + 8 * wg + n);
                        poll();
                        if (!sum()) break;
                    }
                }
#pragma unroll
                for (int i = 0; i < 2; i++) {
                    float2 part = pt[i];
                    part.x += __shfl_xor_sync(0xffffffffu, part.x, 1); part.y += __shfl_xor_sync(0xffffffffu, part.y, 1);
                    part.x += __shfl_xor_sync(0xffffffffu, part.x, 2); part.y += __shfl_xor_sync(0xffffffffu, part.y, 2);
                    ex[i] = cfma(l32q[i], part, ex[i]);
#pragma unroll
                    for (int c = 0; c < 4; c++) { const float2 e = cfma(lam8[i], ex[i], ag[i][c]); ag[i][c] = ex[i]; ex[i] = e; }
                }
                if (t == 0) PROF(4 + 25 * wg);
#pragma unroll
                for (int i = 0; i < 2; i++) {
                    uint32_t cr[2], ci[2], cn[2];
#pragma unroll
                    for (int c = 0; c < 2; c++) { cr[c] = pack2(ag[i][c].x, ag[i][c + 2].x); ci[c] = pack2(ag[i][c].y, ag[i][c + 2].y); scale(i, cr[c], ci[c]); cn[c] = ci[c] ^ 0x80008000u; }
#pragma unroll
                    for (int n = 0; n < 4; n++) {
                        uint32_t* h = &hp[i][16 * (n & 1) + 4 * (n >> 1)];
                        if (fl & (256 << (4 * i + n))) {
#pragma unroll
                            for (int j = 0; j < 8; j++) {
                                const uint32_t x = kr[4 * (n & 1) + (j >> 1)], y = ki[4 * (n & 1) + (j >> 1)];
                                uint32_t& d = h[j + (j & 4)];
                                d = bf_fma2(i ? hi2(x) : lo2(x), (n & 2) ? ci[j & 1] : cr[j & 1], bf_fma2(i ? hi2(y) : lo2(y), (n & 2) ? cr[j & 1] : cn[j & 1], d));
                            }
                        }
                        stsm_x4((i ? hs1 : hs) + n * 4096, h[0], h[1], h[2], h[3]);
                        stsm_x4((i ? hs1 : hs) + n * 4096 + 2048, h[8], h[9], h[10], h[11]);
                        if (4 * i + n == HS0 - 1 || 4 * i + n == 7) {
                            if (4 * i + n == 7 || HF) fence_proxy_async_smem();
                            __syncwarp();
                            warp_arrive(bars + 8 * (BAR_HW + (4 * i + n == 7)));
                        }
                        if (!i && !n && !wg) PROFS(77);
                    }
                }
                if (t == 0) PROF(5 + 25 * wg);
            } else {
                mbar_wait(bars + 8 * BAR_S1, 0);
            }
        }
        if (!main_cta) {
            if (wg) mbar_wait(bars + 8 * BAR_WR, 0);
            fence_proxy_async_smem();
        }
#pragma unroll 1
        for (int ps = wg; ps < 1 + 2 * wg; ps++) {
            if (ps != 1) {
                if (!ps) mbar_wait(bars + 8 * BAR_U, 0);
                if (t == 0) PROF(ps ? 7 : 23);
                radix8(sb, ps, w, lane, 5 + wg);
                if (t == 0) PROF(ps ? 24 : 22);
                if (ps) break;
                bar_sync(5, 128);
                if (FPOS & 1) fence_proxy_async_smem();
            }
            mbar_wait(bars + 8 * (BAR_C + ps), 0);
            phase_c(sb, ps, b + ps == 0, w, lane);
        }
        if (wg == 0) {
            __syncwarp();
            warp_arrive(bars + 8 * BAR_WR);
            if (main_cta) {
                float acc[2][64];
                ring_steps<1>(acc, sb, bars + 8 * BAR_FULL, 31, NS, SLOT_OF(32), 1, 3, 0, 32);
                auto full = [&](int k) { mbar_wait(bars + 8 * (BAR_FULL + SLOT_OF(k)), 1); PROFT(k); };
                auto hstep = [&](int k, int i) {
                    const uint64_t da = make_desc(SLOT_OF(k) * SLOT + i * 8192, 2048, 256, 3), db = make_desc(SLOT_OF(k) * SLOT + 16384, 16, 1024);
                    wgmma_fence();
#pragma unroll
                    for (int j = 0; j < 4; j++) wgmma_n128<1, 0>(acc[i], da + 32 * j, db + 2 * j, 1);
                };
                auto vstep = [&](int k, int i) {
                    const uint64_t da = make_desc(OFF_U - i * 32768 + k * 8192, 16, 1024), db = make_desc(SLOT_OF(64 + (k >> 1)) * SLOT + (k & 1) * 16384, 8192, 1024);
                    if (k || !i) wgmma_fence();
#pragma unroll
                    for (int j = 0; j < 4; j++) wgmma_n128<0, 1>(acc[i], da + 2 * j, db + 128 * j, 1);
                };
                __syncwarp();
                full(63);
                hstep(63, 0);
                bar_sync(4, 256);
                full(64);
                vstep(0, 0);
                vstep(1, 0);
                const CUtensorMap* maps = (const CUtensorMap*)kept(3);
                const uint32_t ob = sb + OFF_U + w * 2048, oa = ob + g * 256 + (((q >> 1) ^ (2 * g & 6)) << 4) + (q & 1) * 8;
#pragma unroll
                for (int i = 0; i < 2; i++) {
                    uint4 e[8];
                    const uint2 sc = lds64u(sb + OFF_SC + (64 * i + 16 * w + 2 * g) * 4);
                    bar_sync(8 + i, 256);
#pragma unroll
                    for (int j = 0; j < 8; j++) e[j] = lds128u(sb + OFF_HS + i * 16384 + (j >> 2) * 8192 + w * 2048 + (j & 3) * 512 + lane * 16);
                    if (i) wgmma_wait<0>();
                    else {
                        full(65);
                        vstep(2, 0);
                        vstep(3, 0);
                        wgmma_commit();
                        hstep(63, 1);
                        vstep(0, 1);
                        wgmma_commit();
                        wgmma_wait<1>();
                    }
#pragma unroll
                    for (int o = 0; o < 64; o++) asm volatile("" : "+f"(acc[i][o]) :: "memory");
                    if (tid == 0) PROF(17 + i);
                    if (tid == 96 && i) PROFG(20);
#pragma unroll
                    for (int c = 0; c < 4; c++) {
#pragma unroll
                        for (int j = 0; j < 8; j++) {
                            const int o = 16 * c + 2 * j;
                            const uint4 e4 = e[2 * c + (j >> 2)];
                            const uint32_t ev = (j & 2) ? ((j & 1) ? e4.w : e4.z) : ((j & 1) ? e4.y : e4.x);
                            const float f = __uint_as_float((j & 1) ? sc.y : sc.x);
                            sts64((oa ^ ((j >> 1) << 5) ^ ((j & 1) * 144)) + c * 8192 - i * 32768, fmaf(f, acc[i][o], bf_lo(ev)), fmaf(f, acc[i][o + 1], bf_hi(ev)));
                        }
                        if (!i && c >= VFIRST && c < 3) {
                            vstep(c + 1, 1);
                            if (c == 2) wgmma_commit();
                        }
                        fence_proxy_async_smem();
                        __syncwarp();
                        if (elect()) tma_store_3d(maps + 9, ob + c * 8192 - i * 32768, 128 * dt + 32 * c, 128 * (tc & 1) + 64 * i + 16 * w, tc >> 1);
                        __syncwarp();
                        if (!i && c < VFIRST && c < 3) {
                            vstep(c + 1, 1);
                            if (c == 2) wgmma_commit();
                        }
                    }
                }
                if (elect()) {
                    bulk_commit();
                    bulk_wait_read();
                }
                if (tid == 0) PROF(19);
                if (tid == 96) { PROF(20); PROFG(4); }
            }
        } else {
            __syncwarp();
            if (tid == 224) PROFG(16);
            if (main_cta) {
                float gs[16];
                uint32_t dk[16], tv[4][4];
#pragma unroll
                for (int j = 0; j < 16; j++) gs[j] = __ldcg(g_gp + (16 * (tc >> 1) + j) * 256 + 128 * (tc & 1) + t);
#pragma unroll
                for (int j = 0; j < 16; j++) dk[j] = ldg32u(P.dskip + 128 * dt + 8 * j + 2 * q);
                const int m0 = ((t >> 2) & 14) + (t >> 6), c0 = 4 * ((t ^ (t >> 3)) & 7);
#pragma unroll
                for (int j = 0; j < 16; j++) {
                    const float a = (float)((j & 3) || c0 ? c0 + (j & 3) : -96) * ((float)(128 * (tc & 1) + 4 * (j & 12) + m0) * 0.024543692606170260f);
                    tv[j >> 2][j & 3] = pack2(__cosf(a), -__sinf(a));
                }
#pragma unroll
                for (int j = 0; j < 4; j++) gs[j] = (gs[j] + gs[j + 4]) + (gs[j + 8] + gs[j + 12]);
                gs[0] = (gs[0] + gs[1]) + (gs[2] + gs[3]);
                const float gg = bf_round(__fdividef(1.f, 1.f + __expf(-bf_round(gs[0])))), og = bf_round(1.f - gg), o2 = fmaxf(2.f * og, 0x1p-40f);
                sts32(sb + OFF_SC + 4 * t, __float_as_uint(o2));
                sts32(sb + OFF_SC + 512 + 4 * t, pack2(__fdividef(gg, o2), og));
                bar_sync(6, 128);
                if (t == 0) PROFX(95);
                auto sign = [](uint32_t n) { return (((n + 1) & 2) << 30) | ((n & 2) << 14); };
                const uint32_t sel = (t & 64) ? 0x1032 : 0x3210;
#pragma unroll
                for (int e = 1; e >= 0; e--) {
                    uint32_t f[4];
#pragma unroll
                    for (int j = 0; j < 4; j++) f[j] = lds16(sb + OFF_SC + 512 + (64 * e + 16 * j + m0) * 4) * 0x10001u;
                    mbar_wait(bars + 8 * (e ? BAR_HD + 1 : BAR_U), !e);
#pragma unroll
                    for (int j = 0; j < 16; j++) {
                        const int k = j & 3, r = j >> 2;
                        uint32_t o[4];
#pragma unroll
                        for (int u = 0; u < 4; u++) {
                            uint32_t v = tv[r][u];
                            if (u == 0 && k < 2 && !c0) v = k ? 0x3f80u : 0x3f003f00u | (t & 64) << 25;
                            if (e) v = ((u & 1) ? __byte_perm(v, 0, 0x1032) : v) ^ sign(u);
                            o[u] = bf_mul2((k & 1) ? __byte_perm(v, 0, sel) : v, f[r] ^ sign(k * m0));
                        }
                        sts128u(sb + OFF_U - e * 32768 + (4 * k + r) * 2048 + t * 16, o[0], o[1], o[2], o[3]);
                        if (P_T && (j & N_T) == N_T) pause(P_T);
                    }
                }
                fence_proxy_async_smem();
                bar_arrive(4, 256);
                if (t == 0) PROF(16);
                const uint32_t xa = sb + OFF_HS + (16 * w + (lane & 15)) * 128 + (((lane >> 4) ^ (lane & 7)) << 4);
#pragma unroll
                for (int e = 0; e < 2; e++) {
                    const uint2 u = lds64u(sb + OFF_SC + 512 + (64 * e + 16 * w + 2 * g) * 4);
                    const uint32_t o0 = __byte_perm(u.x, 0, 0x3232), o1 = __byte_perm(u.y, 0, 0x3232);
                    uint32_t x[8][4];
                    mbar_wait(bars + 8 * (BAR_W + e), 1);
#pragma unroll
                    for (int j = 0; j < 8; j++) {
                        ldsm_x4(x[j], (xa ^ ((j & 3) << 5)) + e * 16384 + (j >> 2) * 8192);
                        if (P_SK && (j & 1)) pause(P_SK);
                    }
#pragma unroll
                    for (int j = 0; j < 8; j++) {
#pragma unroll
                        for (int c = 0; c < 4; c++) x[j][c] = bf_mul2(bf_mul2(x[j][c], dk[2 * j + (c >> 1)]), (c & 1) ? o1 : o0);
                        sts128u(sb + OFF_HS + e * 16384 + (j >> 2) * 8192 + w * 2048 + (j & 3) * 512 + lane * 16, x[j][0], x[j][1], x[j][2], x[j][3]);
                        if (P_SK && (j & 1)) pause(P_SK);
                    }
                    bar_arrive(8 + e, 256);
                    if (t == 0 && !e) PROF(15);
                }
            }
            if (t == 0) {
                const unsigned old = atomicAdd(&g_cnt[CNT_DONE * CS], 1u);
                if (old == 128) { g_cnt[CNT_DONE * CS] = 0; g_cnt[CNT_EPOCH * CS] = (uint32_t)(kept(0) >> 32); }
            }
        }
    } else {
        const int w = warp - 8;
        if (w == 0) {
            bar_sync(7, 64);
            if (!main_cta || !elect()) return;
            {
                int s = 0; uint32_t ph = 0;
#pragma unroll 1
                for (int k = 5; k < 32; k++) {
                    asm volatile(WAIT_LOOP
                        "cp.async.bulk.tensor.4d.shared::cluster.global.mbarrier::complete_tx::bytes [%3], [%5, {%7, %10, %10, %8}], [%2];\n"
                        "cp.async.bulk.tensor.4d.shared::cluster.global.mbarrier::complete_tx::bytes [%4], [%6, {%7, %10, %10, %9}], [%2];\n"
                        "mbarrier.arrive.expect_tx.shared::cta.b64 _, [%2], 32768;\n}"
                        :: "r"(bars + 8 * (BAR_EMPTY + s)), "r"(ph), "r"(bars + 8 * (BAR_FULL + s + (k >> 4) * 5)), "r"(sb + s * SLOT + 16384), "r"(sb + s * SLOT),
                           "l"(&mapX), "l"(&mapB), "r"((k & 15) * 64), "r"(tc * 64), "r"(dt * 8 + (k >> 4) * 64), "r"(0) : "memory");
                    PROFR(k < 19 ? k - 5 : k - 4);
                    if (++s == (k < 15 ? 5 : NS)) { s = 0; ph ^= 1; }
                }
                auto load_x = [&](int e) {
                    mbar_expect_tx(bars + 8 * (BAR_W + e), 16384);
#pragma unroll
                    for (int i = 0; i < 2; i++) tma_load_5d(sb + OFF_HS + e * 16384 + i * 8192, &mapXe, bars + 8 * (BAR_W + e), 128 * dt + 64 * i, 8 * (tc & 1) + 4 * e, tc >> 1);
                };
                const uint8_t* hp = g_hT + tc * 16384;
#pragma unroll 1
                for (int h = 0; h < 32; h++) {
                    asm volatile("{\n.reg .pred q;\n.reg .u32 v, m;\nld.volatile.shared.u32 v, [%10];\nsetp.gt.u32 q, v, %8;\nmov.u32 m, 0;\n" WAIT_LOOP
                        "cp.async.bulk.tensor.3d.shared::cluster.global.mbarrier::complete_tx::bytes [%3], [%5, {%9, %7, %8}], [%2];\n"
                        "@q bra LH;\nLV:\nld.volatile.shared.u32 v, [%10];\nadd.u32 m, m, 1;\nsetp.le.u32 q, v, %8;\nsetp.lt.and.u32 q, m, 4194304, q;\n@q bra LV;\nLH:\n"
                        "cp.async.bulk.shared::cluster.global.mbarrier::complete_tx::bytes [%4], [%6], 16384, [%2];\n"
                        "mbarrier.arrive.expect_tx.shared::cta.b64 _, [%2], 32768;\n}\n}"
                        :: "r"(bars + 8 * (BAR_EMPTY + s)), "r"(ph), "r"(bars + 8 * (BAR_FULL + s)), "r"(sb + s * SLOT + 16384), "r"(sb + s * SLOT),
                           "l"(&mapCre + (h & 1)), "l"(hp), "r"(dt * 128), "r"(h >> 1), "r"(0), "r"(sb + OFF_KEPT + 32) : "memory");
                    PROFR(h + 28);
                    hp += 16 * 16384;
                    if (h == K_XE - 32) load_x(0);
                    if (++s == NS) { s = 0; ph ^= 1; }
                }
                {
                        mbar_wait(bars + 8 * (BAR_F + 2), 0);
#pragma unroll
                        for (int i = 0; i < 2; i++) {
                            const uint32_t pb = bars + 8 * (BAR_XC + i), full = bars + 8 * (BAR_FULL + SLOT_OF(64 + i)), st = sb + SLOT_OF(64 + i) * SLOT;
                            uint32_t rb;
                            asm("mapa.shared::cluster.u32 %0, %1, %2;" : "=r"(rb) : "r"(pb), "r"(~b & 1));
                            asm volatile(WAIT_LOOP "mbarrier.arrive.shared::cluster.b64 _, [%2];\n}" :: "r"(bars + 8 * (BAR_EMPTY + SLOT_OF(64 + i))), "r"(ph), "r"(rb) : "memory");
                            asm volatile(WAIT_LOOP "cp.async.bulk.tensor.3d.shared::cluster.global.mbarrier::complete_tx::bytes.multicast::cluster [%2], [%3, {%5, %6, %7}], [%4], %8;\n}"
                                :: "r"(pb), "r"(1), "r"(st + (b & 1) * 16384), "l"(&mapV), "r"(full), "r"(0), "r"(i * 128 + (b & 1) * 64), "r"((tc >> 1) * 16 + dt * 2), "h"((uint16_t)3) : "memory");
                            mbar_expect_tx(full, SLOT);
                            PROFR(60 + i);
                        }
                    }
                load_x(1);
            }
        } else {
            const unsigned epoch = load_epoch();
            bar_sync(0, 384);
            if (w == 1) {
                bar_arrive(7, 64);
                if (!elect()) return;
                {
                    if (main_cta) {
                        pause(T_XS);
                        bulk_load(sb + OFF_GW, P.gate_w + (b & 15) * 64, 128, bars + 8 * BAR_XC);
#pragma unroll 1
                        for (int c = 0; c < 4; c++) {
                            mbar_expect_tx(bars + 8 * (BAR_XC + c), c ? 8192 : 8192 + 128);
                            tma_load_4d(sb + OFF_U + c * 8192, &mapXs, bars + 8 * (BAR_XC + c), (b & 15) * 64, 0, c, b >> 4);
                            pause(P_XS);
                        }
                    }
                    mbar_wait(bars + 8 * BAR_S1, 0);
                    fence_proxy_async_smem();
                    if (main_cta) {
#pragma unroll 1
                        for (int c = 0; c < 4 * UN; c++) {
                            if (c) pause(PACE_U);
                            tma_store_4d(&mapU0, sb + OFF_U + c * (8192 / UN), (b & 15) * 64, UN == 4 ? 32 * (c >> 2) + 16 * (c & 1) : 32 * (c / UN), UN == 4 ? (c >> 1) & 1 : c % UN, b >> 4);
                        }
                        bulk_store(g_gp + b * 256, sb + OFF_GW, 1024);
                        bulk_commit();
                        bulk_wait0();
                        signal_counter(&g_cnt[CNT_U * CS]);
                    }
                    PROF(9);
                    mbar_expect_tx(bars + 8 * BAR_U, 32768);
                    wait_counter(&g_cnt[CNT_U * CS + (b & (NREP - 1)) * RS], epoch * 128);
                    PROF(11);
#pragma unroll
                    for (int i = 0; i < 8; i++) {
                        if (PACE_L && i && !(i & 1)) pause(PACE_L);
                        tma_load_4d(sb + OFF_U + i * 4096, &mapU2, bars + 8 * BAR_U, 0, 0, (i & 3) * 4, b == 128 ? 1 : b == 0 ? 0 : 2 * b + (i >> 2));
                    }
                    if (main_cta) {
#pragma unroll 1
                        for (int i = 0; i < 2; i++) {
#pragma unroll 1
                            for (int j = 0; j < 2 * HN; j++) {
                                const int hf = j / HN, jj = j % HN;
                                if (j) pause(i ? PACE_HB : PACE_HA);
                                if (j == 0 || j == HS0 * HN / 4) mbar_wait(bars + 8 * (BAR_HW + (j > 0)), i);
                                if (j == 0 && !HF) fence_proxy_async_smem();
                                tma_store_3d(&mapH, sb + OFF_HS + hf * (16384 + i * 18432) + jj * (16384 / HN), 0, 2 * tc + hf, (dt + 8 * i) * 16 + jj * (16 / HN));
                            }
                            bulk_commit();
                            bulk_wait0();
#pragma unroll
                            for (int r = 0; r < NREPH; r++)
                                asm volatile("red.relaxed.gpu.global.add.u64 [%0], %1;" :: "l"(&g_cnt[(CNT_H + 2 * i + (tc >> 3)) * CS + r * RS]), "l"(1ull << (8 * dt)) : "memory");
                            mbar_arrive(bars + 8 * (BAR_HD + i));
                            PROF(i ? 6 : 26);
                            const unsigned* cp = &g_cnt[(CNT_H + 2 * i + (tc & 1)) * CS + ((b >> 1) & (NREPH - 1)) * RS];
#pragma unroll 1
                            for (unsigned n = 0; n < SPIN_LIMIT; n++) {
                                uint64_t v;
                                asm volatile("ld.relaxed.gpu.global.u64 %0, [%1];" : "=l"(v) : "l"(cp) : "memory");
                                v = epoch * 0x0808080808080808ull - v;
                                sts32(sb + OFF_KEPT + 32, (__clzll(__brevll(v)) >> 3) + 8 * i);
                                if (!v) break;
                                if (P_HP) pause(P_HP);
                            }
                            PROF(1 + i);
                        }
                    }
                }
            } else {
                const int ld = (1026 * cls) >> 7, lm = (1026 * ((256 - cls) & 255)) >> 7;
                if (elect() && main_cta) {
                    if (w == 3) {
                        pause(T_W);
#pragma unroll 1
                        for (int i = 0; i < 8; i++) {
                            tma_prefetch_4d(&mapWr + (i & 1), 0, (i & 2) ? lm : ld, i >> 2, 0);
                            pause(200);
                        }
                    } else {
                        pause(T_BA + D_XS * tc);
                        if (tc > 4) tma_prefetch_4d(&mapB, tc * 64, 0, 0, dt * 8);
                        pause(T_B2);
                        bulk_prefetch_l2(((b & 1) ? P.b_im : P.b_re) + (64 + (b >> 1)) * 8192, 16384);
                        pause(T_W0 - D_XS * tc);
                    }
                }
#pragma unroll 1
                for (int ps = 0; ps < 2; ps++) {
                    const uint32_t wb = sb + OFF_W + (1 - ps) * 18432;
                    if (w == 2 && elect()) {
                        const uint32_t bw = bars + 8 * (BAR_W + ps);
                        if (ps && main_cta) mbar_wait(bars + 8 * BAR_HD, 0);
                        mbar_expect_tx(bw, ps ? 18432 : 18432 + 8192);
#pragma unroll 1
                        for (int i = 0; i < 4; i++) {
                            tma_load_4d(wb + (i >> 1) * 4608 + (i & 1) * 9216, &mapWr + (i & 1), bw, 0, i < 2 ? ld : lm, (i < 2 || b == 0) ? ps : 1 - ps, 0);
                            pause(P_W);
                        }
                        if (!ps) bulk_load(sb + OFF_F, c_tab + 8192, 8192, bw);
                        PROFX(85 + ps);
                    }
                    if (w == 3 && ps && main_cta && elect()) {
#pragma unroll 1
                        for (int i = 0; i < 8; i++) {
                            bulk_prefetch_l2(((b & 1) ? P.c_im : P.c_re) + (size_t)(b >> 1) * 16384 + i * 2048, 4096);
                            pause(P_C);
                        }
                    }
                    __syncwarp();
                    mbar_wait(bars + 8 * (BAR_W + ps), 0);
                    if (tid == 320) PROF(ps ? 31 : 10);
#pragma unroll 1
                    for (int u = 0; u < 4; u++) {
                        const int row = 2 * (w - 2) + (u >> 1), pl = u & 1;
                        const uint32_t dp = wb + pl * 9216 + row * 1152, mp = wb + pl * 9216 + 4608 + ((b == 0 && ps == 0) ? (4 - row) & 3 : 3 - row) * 1152;
                        const uint32_t od = dp + ((1026 * cls) & 127), om = mp + ((1026 * (256 - cls)) & 127);
                        uint32_t v[4][8], o[4][4];
#pragma unroll
                        for (int i = 0; i < 8; i++) {
                            const uint4 r = lds128u((i < 4 ? (od & ~15u) + 16 * lane + (i >> 1) * 512 : ((om + 1010) & ~15u) - 16 * lane - ((i >> 1) & 1) * 512) + (i & 1) * 16);
                            uint32_t* d = &v[i >> 1][4 * (i & 1)];
                            d[0] = r.x; d[1] = r.y; d[2] = r.z; d[3] = r.w;
                            if ((P_W0 || P_W1) && (i & 1) && i < 7) pause(ps ? P_W1 : P_W0);
                        }
                        const uint32_t e0 = lds16(om), e1 = lds16(od + 1024);
                        auto fwd = [&](int ws) {
#pragma unroll
                            for (int k = 0; k < 8; k++) o[k >> 2][k & 3] = __byte_perm(v[k >> 2][ws + (k & 3)], v[k >> 2][ws + (k & 3) + 1], (cls & 1) ? 0x5432 : 0x3210);
                        };
                        auto mir = [&](int ws) {
#pragma unroll
                            for (int k = 8; k < 16; k++) o[k >> 2][k & 3] = __byte_perm(v[k >> 2][ws + 3 - (k & 3)], v[k >> 2][ws + 4 - (k & 3)], (cls & 1) ? 0x1032 : 0x3254);
                        };
                        switch ((cls >> 1) & 3) { case 0: fwd(0); break; case 1: fwd(1); break; case 2: fwd(2); break; default: fwd(3); }
                        switch (((1 - cls) >> 1) & 3) { case 0: mir(0); break; case 1: mir(1); break; case 2: mir(2); break; default: mir(3); }
                        if (lane == 0) {
                            o[0][0] = pack2(fmaf(pl ? -0.5f : 0.5f, bf_lo(e0), 0.5f * bf_lo(o[0][0])), bf_hi(o[0][0]));
                            o[2][0] = pack2(fmaf(pl ? -0.5f : 0.5f, bf_lo(e1), 0.5f * bf_lo(o[2][0])), bf_hi(o[2][0]));
                        }
                        __syncwarp();
#pragma unroll
                        for (int i = 0; i < 4; i++)
                        {
                            sts128u((i < 2 ? dp : mp) + (i & 1) * 512 + ((lane * 16) ^ ((lane << 1) & 48)), o[i][0], o[i][1], o[i][2], o[i][3]);
                            if ((P_W0 || P_W1) && (i & 1)) pause(ps ? P_W1 : P_W0);
                        }
                    }
                    if (ps) fence_proxy_async_smem();
                    mbar_arrive(bars + 8 * (BAR_C + ps));
                    if (tid == 320) PROF(ps ? 12 : 28);
                }
                if (!elect()) return;
                if (w == 2) {
                    {
#pragma unroll 1
                        for (int i = 0; i < 8; i++) {
                            if (!(i & 3)) { mbar_wait(bars + 8 * BAR_VW, i >> 2); if (!i && !HF) fence_proxy_async_smem(); }
                            else pause(PACE_V);
                            if (!(real_cls && (i & 1))) tma_store_4d(&mapU2, sb + OFF_U + (i & 1) * 16384 + (i >> 1) * 4096, 0, 0, (i >> 1) * 4, b == 128 ? 1 : 2 * b + (i & 1));
                        }
                        bulk_commit();
                        bulk_wait_read();
                        mbar_arrive(bars + 8 * BAR_U);
                        bulk_wait0();
                        signal_counter(&g_cnt[CNT_V * CS]);
                        PROF(13);
                        if (main_cta) {
                            wait_counter(&g_cnt[CNT_V * CS + (b & (NREP - 1)) * RS], epoch * 129);
                            mbar_arrive(bars + 8 * (BAR_F + 2));
                            PROF(14);
                        }
                    }
                }
            }
        }
    }
}

typedef CUresult (*PFN_encodeTiled)(CUtensorMap*, CUtensorMapDataType, cuuint32_t, void*, const cuuint64_t*, const cuuint64_t*,
                                    const cuuint32_t*, const cuuint32_t*, CUtensorMapInterleave, CUtensorMapSwizzle,
                                    CUtensorMapL2promotion, CUtensorMapFloatOOBfill);

static CUtensorMap make_map(PFN_encodeTiled enc, const void* ptr, int rank, const cuuint64_t* dims, const cuuint64_t* strides, const cuuint32_t* box,
                            CUtensorMapSwizzle sw = CU_TENSOR_MAP_SWIZZLE_128B, CUtensorMapDataType dt = CU_TENSOR_MAP_DATA_TYPE_BFLOAT16) {
    CUtensorMap m;
    cuuint32_t es[5] = {1, 1, 1, 1, 1};
    enc(&m, dt, rank, (void*)ptr, dims, strides, box, es, CU_TENSOR_MAP_INTERLEAVE_NONE,
        sw, CU_TENSOR_MAP_L2_PROMOTION_L2_128B, CU_TENSOR_MAP_FLOAT_OOB_FILL_NONE);
    return m;
}

extern "C" void kernel_launch(void* const* d_in, const int* in_sizes, int n_in, void* d_out, int out_size) {
    const bf16* x = (const bf16*)d_in[0];
    const bf16* wr = (const bf16*)d_in[1];
    const bf16* wi = (const bf16*)d_in[2];
    const bf16* Bre = (const bf16*)d_in[6];
    const bf16* Bim = (const bf16*)d_in[7];
    const bf16* Cre = (const bf16*)d_in[8];
    const bf16* Cim = (const bf16*)d_in[9];

    void* fn = nullptr;
    cudaDriverEntryPointQueryResult st;
    cudaGetDriverEntryPoint("cuTensorMapEncodeTiled", &fn, cudaEnableDefault, &st);
    PFN_encodeTiled enc = (PFN_encodeTiled)fn;
    void *p_hT, *p_U;
    cudaGetSymbolAddress(&p_hT, g_hT);
    cudaGetSymbolAddress(&p_U, g_U);

    Params P;
    P.lam_re = (const bf16*)d_in[4]; P.lam_im = (const bf16*)d_in[5]; P.log_dt = (const bf16*)d_in[10];
    P.dskip = (const bf16*)d_in[11]; P.gate_w = (const bf16*)d_in[12]; P.c_re = Cre; P.c_im = Cim; P.b_re = Bre; P.b_im = Bim; P.x = x;
    P.swapB = Bim < Bre;

    CUtensorMap mB, mX, mCre, mCim, mXs, mU0, mV, mU2, mXe, mO, mWr, mWi, mH;
    {
        cuuint64_t d[4] = {64, 2052, 2, 4}, s[3] = {128, 262656, 525312};
        cuuint32_t bx[4] = {64, 9, 1, 4};
        mWr = make_map(enc, wr, 4, d, s, bx, CU_TENSOR_MAP_SWIZZLE_NONE);
        mWi = make_map(enc, wi, 4, d, s, bx, CU_TENSOR_MAP_SWIZZLE_NONE);
    }
    {
        cuuint64_t d[3] = {128, 32, 256}, s[2] = {1024, 32768};
        cuuint32_t bx[3] = {128, 1, 16 / HN};
        mH = make_map(enc, p_hT, 3, d, s, bx, CU_TENSOR_MAP_SWIZZLE_NONE, CU_TENSOR_MAP_DATA_TYPE_UINT64);
    }
    {
        const bf16* lo = P.swapB ? Bim : Bre; const bf16* hi = P.swapB ? Bre : Bim;
        cuuint64_t d[4] = {1024, 8, 2, 128}, s[3] = {2048, (cuuint64_t)((const char*)hi - (const char*)lo), 16384};
        cuuint32_t bx[4] = {64, 8, 2, 8};
        mB = make_map(enc, lo, 4, d, s, bx);
    }
    {
        cuuint64_t d[4] = {1024, 2, 4, 976}, s[3] = {2048, 32 * 2048, 2 * 2048};
        cuuint32_t bx[4] = {64, 2, 4, 16};
        mX = make_map(enc, x, 4, d, s, bx);
    }
    {
        cuuint64_t d[3] = {64, 1024, 16}, s[2] = {2048, 128};
        cuuint32_t bx[3] = {64, 128, 1};
        mCre = make_map(enc, Cre, 3, d, s, bx);
        mCim = make_map(enc, Cim, 3, d, s, bx);
    }
    {
        cuuint64_t d[3] = {64, 256, 128}, s[2] = {16384, 128};
        cuuint32_t bx[3] = {64, 64, 2};
        mV = make_map(enc, p_U, 3, d, s, bx);
    }
    {
        cuuint64_t d[5] = {1024, 8, 2, 16, 8}, s[4] = {16 * 2048, 8 * 2048, 128 * 2048, 2048};
        cuuint32_t bx[5] = {64, 8, 2, 4, 1};
        mXe = make_map(enc, x, 5, d, s, bx);
    }
    {
        cuuint64_t d[3] = {1024, 256, 8}, s[2] = {8 * 4096, 4096};
        cuuint32_t bx[3] = {32, 16, 1};
        mO = make_map(enc, d_out, 3, d, s, bx, CU_TENSOR_MAP_SWIZZLE_128B, CU_TENSOR_MAP_DATA_TYPE_FLOAT32);
    }
    {
        cuuint64_t d[4] = {1024, 64, 4, 8}, s[3] = {32 * 2048, 8 * 2048, 2048};
        cuuint32_t bx[4] = {64, 64, 1, 1};
        mXs = make_map(enc, x, 4, d, s, bx);
    }
    {
        cuuint64_t d[4] = {1024, 128, 2, 8}, s[3] = {32768, 16384, 2048};
        cuuint32_t bx[4] = {64, UN == 4 ? 16 : 32, UN == 1 ? 2 : 1, 1};
        mU0 = make_map(enc, p_U, 4, d, s, bx);
    }
    {
        cuuint64_t d[4] = {64, 8, 16, 256}, s[3] = {2048, 128, 16384};
        cuuint32_t bx[4] = {64, 8, 4, 1};
        mU2 = make_map(enc, p_U, 4, d, s, bx);
    }
    cudaFuncSetAttribute(fused_kernel, cudaFuncAttributeMaxDynamicSharedMemorySize, SMEM_BYTES);
    fused_kernel<<<130, 384, SMEM_BYTES, cudaStreamPerThread>>>(mB, mX, mXs, mU0, mU2, mXe, mCre, mCim, mV, mO, mWr, mWi, mH, P);
}
```

```cpp
#include <cuda_runtime.h>
#include <cuda_bf16.h>
#include <cuda.h>
#include <stdint.h>
#include <limits.h>

typedef __nv_bfloat16 bf16;

__device__ const __align__(128) uint32_t c_tab[10240] = {
0x3f803f80,0xbf803f80,0x3f803f80,0xbf803f80,0x3f803f80,0xbf803f80,0x3f803f80,0xbf803f80,0x3f803f80,0xbf803f80,0x3f803f80,0xbf803f80,
0x3f803f80,0xbf803f80,0x3f803f80,0xbf803f80,0x3f7f3f80,0xbdc98000,0x3f223f35,0xbf46bf35,0x3f753f7b,0xbe95be48,0x3ef13f0e,0xbf62bf55,
0x3f623f6d,0xbef1bec4,0x3e953ec4,0xbf75bf6d,0x3f463f55,0xbf22bf0e,0x3dc93e48,0xbf7fbf7b,0x3f7b3f80,0xbe488000,0xbe480000,0xbf7bbf80,
0x3f553f6d,0xbf0ebec4,0xbf0ebec4,0xbf55bf6d,0x3f0e3f35,0xbf55bf35,0xbf55bf35,0xbf0ebf35,0x3e483ec4,0xbf7bbf6d,0xbf7bbf6d,0xbe48bec4,
0x3f753f80,0xbe958000,0xbf62bf35,0xbef1bf35,0x3f223f55,0xbf46bf0e,0xbf7fbf7b,0x3dc9be48,0x3dc93ec4,0xbf7fbf6d,0xbf46bf6d,0x3f223ec4,
0xbef1be48,0xbf62bf7b,0xbe95bf0e,0x3f753f55,0x3f6d3f80,0xbec48000,0xbf6dbf80,0x3ec48000,0x3ec43f35,0xbf6dbf35,0xbec4bf35,0x3f6d3f35,
0xbec40000,0xbf6dbf80,0x3ec40000,0x3f6d3f80,0xbf6dbf35,0xbec4bf35,0x3f6d3f35,0x3ec43f35,0x3f623f80,0xbef18000,0xbe95bf35,0x3f753f35,
0x3dc93f0e,0xbf7fbf55,0x3f223e48,0x3f463f7b,0xbf46bec4,0xbf22bf6d,0x3f7f3f6d,0xbdc93ec4,0xbf75bf7b,0x3e95be48,0x3ef13f55,0xbf62bf0e,
0x3f553f80,0xbf0e8000,0x3f0e0000,0x3f553f80,0xbe483ec4,0xbf7bbf6d,0x3f7b3f6d,0xbe483ec4,0xbf7bbf35,0xbe48bf35,0x3e483f35,0xbf7bbf35,
0xbf0ebf6d,0x3f553ec4,0xbf55bec4,0xbf0ebf6d,0x3f463f80,0xbf228000,0x3f7f3f35,0x3dc93f35,0xbef13e48,0xbf62bf7b,0x3e953f55,0xbf75bf0e,
0xbf75bf6d,0x3e95bec4,0xbf62bec4,0xbef1bf6d,0x3dc9bf0e,0x3f7f3f55,0xbf22bf7b,0x3f463e48,0x3f353f80,0xbf358000,0x3f353f80,0xbf358000,
0xbf350000,0xbf35bf80,0xbf350000,0xbf35bf80,0xbf35bf80,0x3f358000,0xbf35bf80,0x3f358000,0x3f350000,0x3f353f80,0x3f350000,0x3f353f80,
0x3f223f80,0xbf468000,0xbdc93f35,0xbf7fbf35,0xbf62be48,0xbef1bf7b,0xbf75bf55,0x3e95bf0e,0xbe95bf6d,0x3f753ec4,0x3ef1bec4,0x3f623f6d,
0x3f7f3f0e,0x3dc93f55,0x3f463f7b,0xbf223e48,0x3f0e3f80,0xbf558000,0xbf550000,0xbf0ebf80,0xbf7bbec4,0xbe48bf6d,0xbe48bf6d,0x3f7b3ec4,
0x3e48bf35,0x3f7b3f35,0x3f7b3f35,0xbe483f35,0x3f553f6d,0xbf0e3ec4,0xbf0e3ec4,0xbf55bf6d,0x3ef13f80,0xbf628000,0xbf75bf35,0x3e95bf35,
0xbf7fbf0e,0x3dc9bf55,0x3f46be48,0x3f223f7b,0x3f22bec4,0x3f463f6d,0x3dc93f6d,0xbf7fbec4,0x3e953f7b,0xbf75be48,0xbf62bf55,0x3ef1bf0e,
0x3ec43f80,0xbf6d8000,0xbec4bf80,0x3f6d8000,0xbf6dbf35,0x3ec4bf35,0x3f6d3f35,0xbec43f35,0x3f6d0000,0x3ec43f80,0xbf6d0000,0xbec4bf80,
0xbec43f35,0xbf6dbf35,0x3ec4bf35,0x3f6d3f35,0x3e953f80,0xbf758000,0x3ef1bf35,0x3f623f35,0xbf46bf55,0x3f22bf0e,0x3dc93f7b,0xbf7fbe48,
0x3f7f3ec4,0xbdc93f6d,0xbf22bf6d,0x3f46bec4,0xbf623e48,0xbef1bf7b,0x3f753f0e,0xbe953f55,0x3e483f80,0xbf7b8000,0x3f7b0000,0x3e483f80,
0xbf0ebf6d,0x3f55bec4,0xbf553ec4,0xbf0ebf6d,0x3f553f35,0xbf0e3f35,0x3f0ebf35,0x3f553f35,0xbf7bbec4,0x3e48bf6d,0xbe483f6d,0xbf7bbec4,
0x3dc93f80,0xbf7f8000,0x3f463f35,0xbf223f35,0xbe95bf7b,0x3f75be48,0xbf62bf0e,0x3ef1bf55,0x3ef13f6d,0xbf623ec4,0x3f753ec4,0xbe953f6d,
0xbf22bf55,0x3f46bf0e,0xbf7fbe48,0x3dc9bf7b,0x3f80,0xbf808000,0x3f80,0xbf808000,0xbf80,0x3f808000,0xbf80,0x3f808000,
0x3f80,0xbf808000,0x3f80,0xbf808000,0xbf80,0x3f808000,0xbf80,0x3f808000,0xbdc93f80,0xbf7f8000,0xbf463f35,0xbf22bf35,
0x3e95bf7b,0x3f753e48,0x3f62bf0e,0x3ef13f55,0xbef13f6d,0xbf62bec4,0xbf753ec4,0xbe95bf6d,0x3f22bf55,0x3f463f0e,0x3f7fbe48,0x3dc93f7b,
0xbe483f80,0xbf7b8000,0xbf7b0000,0x3e48bf80,0x3f0ebf6d,0x3f553ec4,0x3f553ec4,0xbf0e3f6d,0xbf553f35,0xbf0ebf35,0xbf0ebf35,0x3f55bf35,
0x3f7bbec4,0x3e483f6d,0x3e483f6d,0xbf7b3ec4,0xbe953f80,0xbf758000,0xbef1bf35,0x3f62bf35,0x3f46bf55,0x3f223f0e,0xbdc93f7b,0xbf7f3e48,
0xbf7f3ec4,0xbdc9bf6d,0x3f22bf6d,0x3f463ec4,0x3f623e48,0xbef13f7b,0xbf753f0e,0xbe95bf55,0xbec43f80,0xbf6d8000,0x3ec4bf80,0x3f6d8000,
0x3f6dbf35,0x3ec43f35,0xbf6d3f35,0xbec4bf35,0xbf6d0000,0x3ec4bf80,0x3f6d0000,0xbec43f80,0x3ec43f35,0xbf6d3f35,0xbec4bf35,0x3f6dbf35,
0xbef13f80,0xbf628000,0x3f75bf35,0x3e953f35,0x3f7fbf0e,0x3dc93f55,0xbf46be48,0x3f22bf7b,0xbf22bec4,0x3f46bf6d,0xbdc93f6d,0xbf7f3ec4,
0xbe953f7b,0xbf753e48,0x3f62bf55,0x3ef13f0e,0xbf0e3f80,0xbf558000,0x3f550000,0xbf0e3f80,0x3f7bbec4,0xbe483f6d,0x3e48bf6d,0x3f7bbec4,
0xbe48bf35,0x3f7bbf35,0xbf7b3f35,0xbe48bf35,0xbf553f6d,0xbf0ebec4,0x3f0e3ec4,0xbf553f6d,0xbf223f80,0xbf468000,0x3dc93f35,0xbf7f3f35,
0x3f62be48,0xbef13f7b,0x3f75bf55,0x3e953f0e,0x3e95bf6d,0x3f75bec4,0xbef1bec4,0x3f62bf6d,0xbf7f3f0e,0x3dc9bf55,0xbf463f7b,0xbf22be48,
0xbf353f80,0xbf358000,0xbf353f80,0xbf358000,0x3f350000,0xbf353f80,0x3f350000,0xbf353f80,0x3f35bf80,0x3f358000,0x3f35bf80,0x3f358000,
0xbf350000,0x3f35bf80,0xbf350000,0x3f35bf80,0xbf463f80,0xbf228000,0xbf7f3f35,0x3dc9bf35,0x3ef13e48,0xbf623f7b,0xbe953f55,0xbf753f0e,
0x3f75bf6d,0x3e953ec4,0x3f62bec4,0xbef13f6d,0xbdc9bf0e,0x3f7fbf55,0x3f22bf7b,0x3f46be48,0xbf553f80,0xbf0e8000,0xbf0e0000,0x3f55bf80,
0x3e483ec4,0xbf7b3f6d,0xbf7b3f6d,0xbe48bec4,0x3f7bbf35,0xbe483f35,0xbe483f35,0xbf7b3f35,0x3f0ebf6d,0x3f55bec4,0x3f55bec4,0xbf0e3f6d,
0xbf623f80,0xbef18000,0x3e95bf35,0x3f75bf35,0xbdc93f0e,0xbf7f3f55,0xbf223e48,0x3f46bf7b,0x3f46bec4,0xbf223f6d,0xbf7f3f6d,0xbdc9bec4,
0x3f75bf7b,0x3e953e48,0xbef13f55,0xbf623f0e,0xbf6d3f80,0xbec48000,0x3f6dbf80,0x3ec48000,0xbec43f35,0xbf6d3f35,0x3ec4bf35,0x3f6dbf35,
0x3ec40000,0xbf6d3f80,0xbec40000,0x3f6dbf80,0x3f6dbf35,0xbec43f35,0xbf6d3f35,0x3ec4bf35,0xbf753f80,0xbe958000,0x3f62bf35,0xbef13f35,
0xbf223f55,0xbf463f0e,0x3f7fbf7b,0x3dc93e48,0xbdc93ec4,0xbf7f3f6d,0x3f46bf6d,0x3f22bec4,0x3ef1be48,0xbf623f7b,0x3e95bf0e,0x3f75bf55,
0xbf7b3f80,0xbe488000,0x3e480000,0xbf7b3f80,0xbf553f6d,0xbf0e3ec4,0x3f0ebec4,0xbf553f6d,0xbf0e3f35,0xbf553f35,0x3f55bf35,0xbf0e3f35,
0xbe483ec4,0xbf7b3f6d,0x3f7bbf6d,0xbe483ec4,0xbf7f3f80,0xbdc98000,0xbf223f35,0xbf463f35,0xbf753f7b,0xbe953e48,0xbef13f0e,0xbf623f55,
0xbf623f6d,0xbef13ec4,0xbe953ec4,0xbf753f6d,0xbf463f55,0xbf223f0e,0xbdc93e48,0xbf7f3f7b,0x3f803f80,0xbf803f80,0x3f803f80,0xbf803f80,
0x3f803f80,0xbf803f80,0x3f803f80,0xbf803f80,0x3f803f80,0xbf803f80,0x3f803f80,0xbf803f80,0x3f803f80,0xbf803f80,0x3f803f80,0xbf803f80,
0xbdc90000,0xbf7fbf80,0xbf46bf35,0xbf22bf35,0xbe95be48,0xbf75bf7b,0xbf62bf55,0xbef1bf0e,0xbef1bec4,0xbf62bf6d,0xbf75bf6d,0xbe95bec4,
0xbf22bf0e,0xbf46bf55,0xbf7fbf7b,0xbdc9be48,0xbf7bbf80,0x3e488000,0x3e480000,0x3f7b3f80,0xbf55bf6d,0x3f0e3ec4,0x3f0e3ec4,0x3f553f6d,
0xbf0ebf35,0x3f553f35,0x3f553f35,0x3f0e3f35,0xbe48bec4,0x3f7b3f6d,0x3f7b3f6d,0x3e483ec4,0x3e950000,0x3f753f80,0x3ef13f35,0xbf62bf35,
0x3f463f0e,0x3f223f55,0xbdc93e48,0xbf7fbf7b,0x3f7f3f6d,0x3dc93ec4,0xbf22bec4,0xbf46bf6d,0x3f623f7b,0xbef1be48,0xbf75bf55,0xbe95bf0e,
0x3f6d3f80,0xbec48000,0xbf6dbf80,0x3ec48000,0x3ec43f35,0xbf6dbf35,0xbec4bf35,0x3f6d3f35,0xbec40000,0xbf6dbf80,0x3ec40000,0x3f6d3f80,
0xbf6dbf35,0xbec4bf35,0x3f6d3f35,0x3ec43f35,0xbef10000,0xbf62bf80,0x3f753f35,0x3e953f35,0xbf7fbf55,0xbdc9bf0e,0x3f463f7b,0xbf22be48,
0xbf22bf6d,0x3f463ec4,0xbdc93ec4,0xbf7fbf6d,0x3e95be48,0x3f753f7b,0xbf62bf0e,0xbef1bf55,0xbf55bf80,0x3f0e8000,0xbf0e0000,0xbf55bf80,
0x3e48bec4,0x3f7b3f6d,0xbf7bbf6d,0x3e48bec4,0x3f7b3f35,0x3e483f35,0xbe48bf35,0x3f7b3f35,0x3f0e3f6d,0xbf55bec4,0x3f553ec4,0x3f0e3f6d,
0x3f220000,0x3f463f80,0xbdc9bf35,0x3f7f3f35,0x3f623f7b,0xbef13e48,0x3f753f0e,0x3e953f55,0xbe953ec4,0xbf75bf6d,0x3ef13f6d,0xbf62bec4,
0xbf7fbf55,0x3dc9bf0e,0xbf46be48,0xbf22bf7b,0x3f353f80,0xbf358000,0x3f353f80,0xbf358000,0xbf350000,0xbf35bf80,0xbf350000,0xbf35bf80,
0xbf35bf80,0x3f358000,0xbf35bf80,0x3f358000,0x3f350000,0x3f353f80,0x3f350000,0x3f353f80,0xbf460000,0xbf22bf80,0xbf7fbf35,0x3dc9bf35,
0xbef1bf7b,0x3f623e48,0x3e95bf0e,0x3f753f55,0x3f753ec4,0x3e953f6d,0x3f623f6d,0xbef13ec4,0x3dc93f55,0xbf7fbf0e,0xbf223e48,0xbf46bf7b,
0xbf0ebf80,0x3f558000,0x3f550000,0x3f0e3f80,0x3f7b3ec4,0x3e483f6d,0x3e483f6d,0xbf7bbec4,0xbe483f35,0xbf7bbf35,0xbf7bbf35,0x3e48bf35,
0xbf55bf6d,0x3f0ebec4,0x3f0ebec4,0x3f553f6d,0x3f620000,0x3ef13f80,0xbe953f35,0xbf75bf35,0xbdc93f55,0xbf7fbf0e,0xbf22bf7b,0x3f46be48,
0xbf46bf6d,0x3f22bec4,0x3f7f3ec4,0x3dc93f6d,0x3f753e48,0x3e953f7b,0xbef13f0e,0xbf62bf55,0x3ec43f80,0xbf6d8000,0xbec4bf80,0x3f6d8000,
0xbf6dbf35,0x3ec4bf35,0x3f6d3f35,0xbec43f35,0x3f6d0000,0x3ec43f80,0xbf6d0000,0xbec4bf80,0xbec43f35,0xbf6dbf35,0x3ec4bf35,0x3f6d3f35,
0xbf750000,0xbe95bf80,0x3f623f35,0xbef13f35,0x3f22bf0e,0x3f463f55,0xbf7fbe48,0xbdc9bf7b,0xbdc93f6d,0xbf7fbec4,0x3f46bec4,0x3f223f6d,
0xbef1bf7b,0x3f62be48,0xbe953f55,0xbf75bf0e,0xbe48bf80,0x3f7b8000,0xbf7b0000,0xbe48bf80,0x3f0e3f6d,0xbf553ec4,0x3f55bec4,0x3f0e3f6d,
0xbf55bf35,0x3f0ebf35,0xbf0e3f35,0xbf55bf35,0x3f7b3ec4,0xbe483f6d,0x3e48bf6d,0x3f7b3ec4,0x3f7f0000,0x3dc93f80,0x3f22bf35,0x3f463f35,
0xbf753e48,0xbe95bf7b,0xbef13f55,0xbf62bf0e,0x3f62bec4,0x3ef13f6d,0x3e95bf6d,0x3f753ec4,0xbf463f0e,0xbf22bf55,0xbdc93f7b,0xbf7fbe48,
0x3f80,0xbf808000,0x3f80,0xbf808000,0xbf80,0x3f808000,0xbf80,0x3f808000,0x3f80,0xbf808000,0x3f80,0xbf808000,
0xbf80,0x3f808000,0xbf80,0x3f808000,0xbf7f0000,0x3dc9bf80,0xbf22bf35,0x3f46bf35,0x3f753e48,0xbe953f7b,0x3ef13f55,0xbf623f0e,
0xbf62bec4,0x3ef1bf6d,0xbe95bf6d,0x3f75bec4,0x3f463f0e,0xbf223f55,0x3dc93f7b,0xbf7f3e48,0x3e48bf80,0x3f7b8000,0x3f7b0000,0xbe483f80,
0xbf0e3f6d,0xbf55bec4,0xbf55bec4,0x3f0ebf6d,0x3f55bf35,0x3f0e3f35,0x3f0e3f35,0xbf553f35,0xbf7b3ec4,0xbe48bf6d,0xbe48bf6d,0x3f7bbec4,
0x3f750000,0xbe953f80,0xbf623f35,0xbef1bf35,0xbf22bf0e,0x3f46bf55,0x3f7fbe48,0xbdc93f7b,0x3dc93f6d,0xbf7f3ec4,0xbf46bec4,0x3f22bf6d,
0x3ef1bf7b,0x3f623e48,0x3e953f55,0xbf753f0e,0xbec43f80,0xbf6d8000,0x3ec4bf80,0x3f6d8000,0x3f6dbf35,0x3ec43f35,0xbf6d3f35,0xbec4bf35,
0xbf6d0000,0x3ec4bf80,0x3f6d0000,0xbec43f80,0x3ec43f35,0xbf6d3f35,0xbec4bf35,0x3f6dbf35,0xbf620000,0x3ef1bf80,0x3e953f35,0xbf753f35,
0x3dc93f55,0xbf7f3f0e,0x3f22bf7b,0x3f463e48,0x3f46bf6d,0x3f223ec4,0xbf7f3ec4,0x3dc9bf6d,0xbf753e48,0x3e95bf7b,0x3ef13f0e,0xbf623f55,
0x3f0ebf80,0x3f558000,0xbf550000,0x3f0ebf80,0xbf7b3ec4,0x3e48bf6d,0xbe483f6d,0xbf7b3ec4,0x3e483f35,0xbf7b3f35,0x3f7bbf35,0x3e483f35,
0x3f55bf6d,0x3f0e3ec4,0xbf0ebec4,0x3f55bf6d,0x3f460000,0xbf223f80,0x3f7fbf35,0x3dc93f35,0x3ef1bf7b,0x3f62be48,0xbe95bf0e,0x3f75bf55,
0xbf753ec4,0x3e95bf6d,0xbf623f6d,0xbef1bec4,0xbdc93f55,0xbf7f3f0e,0x3f223e48,0xbf463f7b,0xbf353f80,0xbf358000,0xbf353f80,0xbf358000,
0x3f350000,0xbf353f80,0x3f350000,0xbf353f80,0x3f35bf80,0x3f358000,0x3f35bf80,0x3f358000,0xbf350000,0x3f35bf80,0xbf350000,0x3f35bf80,
0xbf220000,0x3f46bf80,0x3dc9bf35,0x3f7fbf35,0xbf623f7b,0xbef1be48,0xbf753f0e,0x3e95bf55,0x3e953ec4,0xbf753f6d,0xbef13f6d,0xbf623ec4,
0x3f7fbf55,0x3dc93f0e,0x3f46be48,0xbf223f7b,0x3f55bf80,0x3f0e8000,0x3f0e0000,0xbf553f80,0xbe48bec4,0x3f7bbf6d,0x3f7bbf6d,0x3e483ec4,
0xbf7b3f35,0x3e48bf35,0x3e48bf35,0x3f7bbf35,0xbf0e3f6d,0xbf553ec4,0xbf553ec4,0x3f0ebf6d,0x3ef10000,0xbf623f80,0xbf753f35,0x3e95bf35,
0x3f7fbf55,0xbdc93f0e,0xbf463f7b,0xbf223e48,0x3f22bf6d,0x3f46bec4,0x3dc93ec4,0xbf7f3f6d,0xbe95be48,0x3f75bf7b,0x3f62bf0e,0xbef13f55,
0xbf6d3f80,0xbec48000,0x3f6dbf80,0x3ec48000,0xbec43f35,0xbf6d3f35,0x3ec4bf35,0x3f6dbf35,0x3ec40000,0xbf6d3f80,0xbec40000,0x3f6dbf80,
0x3f6dbf35,0xbec43f35,0xbf6d3f35,0x3ec4bf35,0xbe950000,0x3f75bf80,0xbef13f35,0xbf623f35,0xbf463f0e,0x3f22bf55,0x3dc93e48,0xbf7f3f7b,
0xbf7f3f6d,0x3dc9bec4,0x3f22bec4,0xbf463f6d,0xbf623f7b,0xbef13e48,0x3f75bf55,0xbe953f0e,0x3f7bbf80,0x3e488000,0xbe480000,0x3f7bbf80,
0x3f55bf6d,0x3f0ebec4,0xbf0e3ec4,0x3f55bf6d,0x3f0ebf35,0x3f55bf35,0xbf553f35,0x3f0ebf35,0x3e48bec4,0x3f7bbf6d,0xbf7b3f6d,0x3e48bec4,
0x3dc90000,0xbf7f3f80,0x3f46bf35,0xbf223f35,0x3e95be48,0xbf753f7b,0x3f62bf55,0xbef13f0e,0x3ef1bec4,0xbf623f6d,0x3f75bf6d,0xbe953ec4,
0x3f22bf0e,0xbf463f55,0x3f7fbf7b,0xbdc93e48,0x3f803f80,0xbf803f80,0x3f803f80,0xbf803f80,0x3f803f80,0xbf803f80,0x3f803f80,0xbf803f80,
0x3f803f80,0xbf803f80,0x3f803f80,0xbf803f80,0x3f803f80,0xbf803f80,0x3f803f80,0xbf803f80,0xbf7fbf80,0x3dc98000,0xbf22bf35,0x3f463f35,
0xbf75bf7b,0x3e953e48,0xbef1bf0e,0x3f623f55,0xbf62bf6d,0x3ef13ec4,0xbe95bec4,0x3f753f6d,0xbf46bf55,0x3f223f0e,0xbdc9be48,0x3f7f3f7b,
0x3f7b3f80,0xbe488000,0xbe480000,0xbf7bbf80,0x3f553f6d,0xbf0ebec4,0xbf0ebec4,0xbf55bf6d,0x3f0e3f35,0xbf55bf35,0xbf55bf35,0xbf0ebf35,
0x3e483ec4,0xbf7bbf6d,0xbf7bbf6d,0xbe48bec4,0xbf75bf80,0x3e958000,0x3f623f35,0x3ef13f35,0xbf22bf55,0x3f463f0e,0x3f7f3f7b,0xbdc93e48,
0xbdc9bec4,0x3f7f3f6d,0x3f463f6d,0xbf22bec4,0x3ef13e48,0x3f623f7b,0x3e953f0e,0xbf75bf55,0x3f6d3f80,0xbec48000,0xbf6dbf80,0x3ec48000,
0x3ec43f35,0xbf6dbf35,0xbec4bf35,0x3f6d3f35,0xbec40000,0xbf6dbf80,0x3ec40000,0x3f6d3f80,0xbf6dbf35,0xbec4bf35,0x3f6d3f35,0x3ec43f35,
0xbf62bf80,0x3ef18000,0x3e953f35,0xbf75bf35,0xbdc9bf0e,0x3f7f3f55,0xbf22be48,0xbf46bf7b,0x3f463ec4,0x3f223f6d,0xbf7fbf6d,0x3dc9bec4,
0x3f753f7b,0xbe953e48,0xbef1bf55,0x3f623f0e,0x3f553f80,0xbf0e8000,0x3f0e0000,0x3f553f80,0xbe483ec4,0xbf7bbf6d,0x3f7b3f6d,0xbe483ec4,
0xbf7bbf35,0xbe48bf35,0x3e483f35,0xbf7bbf35,0xbf0ebf6d,0x3f553ec4,0xbf55bec4,0xbf0ebf6d,0xbf46bf80,0x3f228000,0xbf7fbf35,0xbdc9bf35,
0x3ef1be48,0x3f623f7b,0xbe95bf55,0x3f753f0e,0x3f753f6d,0xbe953ec4,0x3f623ec4,0x3ef13f6d,0xbdc93f0e,0xbf7fbf55,0x3f223f7b,0xbf46be48,
0x3f353f80,0xbf358000,0x3f353f80,0xbf358000,0xbf350000,0xbf35bf80,0xbf350000,0xbf35bf80,0xbf35bf80,0x3f358000,0xbf35bf80,0x3f358000,
0x3f350000,0x3f353f80,0x3f350000,0x3f353f80,0xbf22bf80,0x3f468000,0x3dc9bf35,0x3f7f3f35,0x3f623e48,0x3ef13f7b,0x3f753f55,0xbe953f0e,
0x3e953f6d,0xbf75bec4,0xbef13ec4,0xbf62bf6d,0xbf7fbf0e,0xbdc9bf55,0xbf46bf7b,0x3f22be48,0x3f0e3f80,0xbf558000,0xbf550000,0xbf0ebf80,
0xbf7bbec4,0xbe48bf6d,0xbe48bf6d,0x3f7b3ec4,0x3e48bf35,0x3f7b3f35,0x3f7b3f35,0xbe483f35,0x3f553f6d,0xbf0e3ec4,0xbf0e3ec4,0xbf55bf6d,
0xbef1bf80,0x3f628000,0x3f753f35,0xbe953f35,0x3f7f3f0e,0xbdc93f55,0xbf463e48,0xbf22bf7b,0xbf223ec4,0xbf46bf6d,0xbdc9bf6d,0x3f7f3ec4,
0xbe95bf7b,0x3f753e48,0x3f623f55,0xbef13f0e,0x3ec43f80,0xbf6d8000,0xbec4bf80,0x3f6d8000,0xbf6dbf35,0x3ec4bf35,0x3f6d3f35,0xbec43f35,
0x3f6d0000,0x3ec43f80,0xbf6d0000,0xbec4bf80,0xbec43f35,0xbf6dbf35,0x3ec4bf35,0x3f6d3f35,0xbe95bf80,0x3f758000,0xbef13f35,0xbf62bf35,
0x3f463f55,0xbf223f0e,0xbdc9bf7b,0x3f7f3e48,0xbf7fbec4,0x3dc9bf6d,0x3f223f6d,0xbf463ec4,0x3f62be48,0x3ef13f7b,0xbf75bf0e,0x3e95bf55,
0x3e483f80,0xbf7b8000,0x3f7b0000,0x3e483f80,0xbf0ebf6d,0x3f55bec4,0xbf553ec4,0xbf0ebf6d,0x3f553f35,0xbf0e3f35,0x3f0ebf35,0x3f553f35,
0xbf7bbec4,0x3e48bf6d,0xbe483f6d,0xbf7bbec4,0xbdc9bf80,0x3f7f8000,0xbf46bf35,0x3f22bf35,0x3e953f7b,0xbf753e48,0x3f623f0e,0xbef13f55,
0xbef1bf6d,0x3f62bec4,0xbf75bec4,0x3e95bf6d,0x3f223f55,0xbf463f0e,0x3f7f3e48,0xbdc93f7b,0x3f80,0xbf808000,0x3f80,0xbf808000,
0xbf80,0x3f808000,0xbf80,0x3f808000,0x3f80,0xbf808000,0x3f80,0xbf808000,0xbf80,0x3f808000,0xbf80,0x3f808000,
0x3dc9bf80,0x3f7f8000,0x3f46bf35,0x3f223f35,0xbe953f7b,0xbf75be48,0xbf623f0e,0xbef1bf55,0x3ef1bf6d,0x3f623ec4,0x3f75bec4,0x3e953f6d,
0xbf223f55,0xbf46bf0e,0xbf7f3e48,0xbdc9bf7b,0xbe483f80,0xbf7b8000,0xbf7b0000,0x3e48bf80,0x3f0ebf6d,0x3f553ec4,0x3f553ec4,0xbf0e3f6d,
0xbf553f35,0xbf0ebf35,0xbf0ebf35,0x3f55bf35,0x3f7bbec4,0x3e483f6d,0x3e483f6d,0xbf7b3ec4,0x3e95bf80,0x3f758000,0x3ef13f35,0xbf623f35,
0xbf463f55,0xbf22bf0e,0x3dc9bf7b,0x3f7fbe48,0x3f7fbec4,0x3dc93f6d,0xbf223f6d,0xbf46bec4,0xbf62be48,0x3ef1bf7b,0x3f75bf0e,0x3e953f55,
0xbec43f80,0xbf6d8000,0x3ec4bf80,0x3f6d8000,0x3f6dbf35,0x3ec43f35,0xbf6d3f35,0xbec4bf35,0xbf6d0000,0x3ec4bf80,0x3f6d0000,0xbec43f80,
0x3ec43f35,0xbf6d3f35,0xbec4bf35,0x3f6dbf35,0x3ef1bf80,0x3f628000,0xbf753f35,0xbe95bf35,0xbf7f3f0e,0xbdc9bf55,0x3f463e48,0xbf223f7b,
0x3f223ec4,0xbf463f6d,0x3dc9bf6d,0x3f7fbec4,0x3e95bf7b,0x3f75be48,0xbf623f55,0xbef1bf0e,0xbf0e3f80,0xbf558000,0x3f550000,0xbf0e3f80,
0x3f7bbec4,0xbe483f6d,0x3e48bf6d,0x3f7bbec4,0xbe48bf35,0x3f7bbf35,0xbf7b3f35,0xbe48bf35,0xbf553f6d,0xbf0ebec4,0x3f0e3ec4,0xbf553f6d,
0x3f22bf80,0x3f468000,0xbdc9bf35,0x3f7fbf35,0xbf623e48,0x3ef1bf7b,0xbf753f55,0xbe95bf0e,0xbe953f6d,0xbf753ec4,0x3ef13ec4,0xbf623f6d,
0x3f7fbf0e,0xbdc93f55,0x3f46bf7b,0x3f223e48,0xbf353f80,0xbf358000,0xbf353f80,0xbf358000,0x3f350000,0xbf353f80,0x3f350000,0xbf353f80,
0x3f35bf80,0x3f358000,0x3f35bf80,0x3f358000,0xbf350000,0x3f35bf80,0xbf350000,0x3f35bf80,0x3f46bf80,0x3f228000,0x3f7fbf35,0xbdc93f35,
0xbef1be48,0x3f62bf7b,0x3e95bf55,0x3f75bf0e,0xbf753f6d,0xbe95bec4,0xbf623ec4,0x3ef1bf6d,0x3dc93f0e,0xbf7f3f55,0xbf223f7b,0xbf463e48,
0xbf553f80,0xbf0e8000,0xbf0e0000,0x3f55bf80,0x3e483ec4,0xbf7b3f6d,0xbf7b3f6d,0xbe48bec4,0x3f7bbf35,0xbe483f35,0xbe483f35,0xbf7b3f35,
0x3f0ebf6d,0x3f55bec4,0x3f55bec4,0xbf0e3f6d,0x3f62bf80,0x3ef18000,0xbe953f35,0xbf753f35,0x3dc9bf0e,0x3f7fbf55,0x3f22be48,0xbf463f7b,
0xbf463ec4,0x3f22bf6d,0x3f7fbf6d,0x3dc93ec4,0xbf753f7b,0xbe95be48,0x3ef1bf55,0x3f62bf0e,0xbf6d3f80,0xbec48000,0x3f6dbf80,0x3ec48000,
0xbec43f35,0xbf6d3f35,0x3ec4bf35,0x3f6dbf35,0x3ec40000,0xbf6d3f80,0xbec40000,0x3f6dbf80,0x3f6dbf35,0xbec43f35,0xbf6d3f35,0x3ec4bf35,
0x3f75bf80,0x3e958000,0xbf623f35,0x3ef1bf35,0x3f22bf55,0x3f46bf0e,0xbf7f3f7b,0xbdc9be48,0x3dc9bec4,0x3f7fbf6d,0xbf463f6d,0xbf223ec4,
0xbef13e48,0x3f62bf7b,0xbe953f0e,0xbf753f55,0xbf7b3f80,0xbe488000,0x3e480000,0xbf7b3f80,0xbf553f6d,0xbf0e3ec4,0x3f0ebec4,0xbf553f6d,
0xbf0e3f35,0xbf553f35,0x3f55bf35,0xbf0e3f35,0xbe483ec4,0xbf7b3f6d,0x3f7bbf6d,0xbe483ec4,0x3f7fbf80,0x3dc98000,0x3f22bf35,0x3f46bf35,
0x3f75bf7b,0x3e95be48,0x3ef1bf0e,0x3f62bf55,0x3f62bf6d,0x3ef1bec4,0x3e95bec4,0x3f75bf6d,0x3f46bf55,0x3f22bf0e,0x3dc9be48,0x3f7fbf7b,
0x3f803f80,0xbf803f80,0x3f803f80,0xbf803f80,0x3f803f80,0xbf803f80,0x3f803f80,0xbf803f80,0x3f803f80,0xbf803f80,0x3f803f80,0xbf803f80,
0x3f803f80,0xbf803f80,0x3f803f80,0xbf803f80,0x3dc90000,0x3f7f3f80,0x3f463f35,0x3f223f35,0x3e953e48,0x3f753f7b,0x3f623f55,0x3ef13f0e,
0x3ef13ec4,0x3f623f6d,0x3f753f6d,0x3e953ec4,0x3f223f0e,0x3f463f55,0x3f7f3f7b,0x3dc93e48,0xbf7bbf80,0x3e488000,0x3e480000,0x3f7b3f80,
0xbf55bf6d,0x3f0e3ec4,0x3f0e3ec4,0x3f553f6d,0xbf0ebf35,0x3f553f35,0x3f553f35,0x3f0e3f35,0xbe48bec4,0x3f7b3f6d,0x3f7b3f6d,0x3e483ec4,
0xbe950000,0xbf75bf80,0xbef1bf35,0x3f623f35,0xbf46bf0e,0xbf22bf55,0x3dc9be48,0x3f7f3f7b,0xbf7fbf6d,0xbdc9bec4,0x3f223ec4,0x3f463f6d,
0xbf62bf7b,0x3ef13e48,0x3f753f55,0x3e953f0e,0x3f6d3f80,0xbec48000,0xbf6dbf80,0x3ec48000,0x3ec43f35,0xbf6dbf35,0xbec4bf35,0x3f6d3f35,
0xbec40000,0xbf6dbf80,0x3ec40000,0x3f6d3f80,0xbf6dbf35,0xbec4bf35,0x3f6d3f35,0x3ec43f35,0x3ef10000,0x3f623f80,0xbf75bf35,0xbe95bf35,
0x3f7f3f55,0x3dc93f0e,0xbf46bf7b,0x3f223e48,0x3f223f6d,0xbf46bec4,0x3dc9bec4,0x3f7f3f6d,0xbe953e48,0xbf75bf7b,0x3f623f0e,0x3ef13f55,
0xbf55bf80,0x3f0e8000,0xbf0e0000,0xbf55bf80,0x3e48bec4,0x3f7b3f6d,0xbf7bbf6d,0x3e48bec4,0x3f7b3f35,0x3e483f35,0xbe48bf35,0x3f7b3f35,
0x3f0e3f6d,0xbf55bec4,0x3f553ec4,0x3f0e3f6d,0xbf220000,0xbf46bf80,0x3dc93f35,0xbf7fbf35,0xbf62bf7b,0x3ef1be48,0xbf75bf0e,0xbe95bf55,
0x3e95bec4,0x3f753f6d,0xbef1bf6d,0x3f623ec4,0x3f7f3f55,0xbdc93f0e,0x3f463e48,0x3f223f7b,0x3f353f80,0xbf358000,0x3f353f80,0xbf358000,
0xbf350000,0xbf35bf80,0xbf350000,0xbf35bf80,0xbf35bf80,0x3f358000,0xbf35bf80,0x3f358000,0x3f350000,0x3f353f80,0x3f350000,0x3f353f80,
0x3f460000,0x3f223f80,0x3f7f3f35,0xbdc93f35,0x3ef13f7b,0xbf62be48,0xbe953f0e,0xbf75bf55,0xbf75bec4,0xbe95bf6d,0xbf62bf6d,0x3ef1bec4,
0xbdc9bf55,0x3f7f3f0e,0x3f22be48,0x3f463f7b,0xbf0ebf80,0x3f558000,0x3f550000,0x3f0e3f80,0x3f7b3ec4,0x3e483f6d,0x3e483f6d,0xbf7bbec4,
0xbe483f35,0xbf7bbf35,0xbf7bbf35,0x3e48bf35,0xbf55bf6d,0x3f0ebec4,0x3f0ebec4,0x3f553f6d,0xbf620000,0xbef1bf80,0x3e95bf35,0x3f753f35,
0x3dc9bf55,0x3f7f3f0e,0x3f223f7b,0xbf463e48,0x3f463f6d,0xbf223ec4,0xbf7fbec4,0xbdc9bf6d,0xbf75be48,0xbe95bf7b,0x3ef1bf0e,0x3f623f55,
0x3ec43f80,0xbf6d8000,0xbec4bf80,0x3f6d8000,0xbf6dbf35,0x3ec4bf35,0x3f6d3f35,0xbec43f35,0x3f6d0000,0x3ec43f80,0xbf6d0000,0xbec4bf80,
0xbec43f35,0xbf6dbf35,0x3ec4bf35,0x3f6d3f35,0x3f750000,0x3e953f80,0xbf62bf35,0x3ef1bf35,0xbf223f0e,0xbf46bf55,0x3f7f3e48,0x3dc93f7b,
0x3dc9bf6d,0x3f7f3ec4,0xbf463ec4,0xbf22bf6d,0x3ef13f7b,0xbf623e48,0x3e95bf55,0x3f753f0e,0xbe48bf80,0x3f7b8000,0xbf7b0000,0xbe48bf80,
0x3f0e3f6d,0xbf553ec4,0x3f55bec4,0x3f0e3f6d,0xbf55bf35,0x3f0ebf35,0xbf0e3f35,0xbf55bf35,0x3f7b3ec4,0xbe483f6d,0x3e48bf6d,0x3f7b3ec4,
0xbf7f0000,0xbdc9bf80,0xbf223f35,0xbf46bf35,0x3f75be48,0x3e953f7b,0x3ef1bf55,0x3f623f0e,0xbf623ec4,0xbef1bf6d,0xbe953f6d,0xbf75bec4,
0x3f46bf0e,0x3f223f55,0x3dc9bf7b,0x3f7f3e48,0x3f80,0xbf808000,0x3f80,0xbf808000,0xbf80,0x3f808000,0xbf80,0x3f808000,
0x3f80,0xbf808000,0x3f80,0xbf808000,0xbf80,0x3f808000,0xbf80,0x3f808000,0x3f7f0000,0xbdc93f80,0x3f223f35,0xbf463f35,
0xbf75be48,0x3e95bf7b,0xbef1bf55,0x3f62bf0e,0x3f623ec4,0xbef13f6d,0x3e953f6d,0xbf753ec4,0xbf46bf0e,0x3f22bf55,0xbdc9bf7b,0x3f7fbe48,
0x3e48bf80,0x3f7b8000,0x3f7b0000,0xbe483f80,0xbf0e3f6d,0xbf55bec4,0xbf55bec4,0x3f0ebf6d,0x3f55bf35,0x3f0e3f35,0x3f0e3f35,0xbf553f35,
0xbf7b3ec4,0xbe48bf6d,0xbe48bf6d,0x3f7bbec4,0xbf750000,0x3e95bf80,0x3f62bf35,0x3ef13f35,0x3f223f0e,0xbf463f55,0xbf7f3e48,0x3dc9bf7b,
0xbdc9bf6d,0x3f7fbec4,0x3f463ec4,0xbf223f6d,0xbef13f7b,0xbf62be48,0xbe95bf55,0x3f75bf0e,0xbec43f80,0xbf6d8000,0x3ec4bf80,0x3f6d8000,
0x3f6dbf35,0x3ec43f35,0xbf6d3f35,0xbec4bf35,0xbf6d0000,0x3ec4bf80,0x3f6d0000,0xbec43f80,0x3ec43f35,0xbf6d3f35,0xbec4bf35,0x3f6dbf35,
0x3f620000,0xbef13f80,0xbe95bf35,0x3f75bf35,0xbdc9bf55,0x3f7fbf0e,0xbf223f7b,0xbf46be48,0xbf463f6d,0xbf22bec4,0x3f7fbec4,0xbdc93f6d,
0x3f75be48,0xbe953f7b,0xbef1bf0e,0x3f62bf55,0x3f0ebf80,0x3f558000,0xbf550000,0x3f0ebf80,0xbf7b3ec4,0x3e48bf6d,0xbe483f6d,0xbf7b3ec4,
0x3e483f35,0xbf7b3f35,0x3f7bbf35,0x3e483f35,0x3f55bf6d,0x3f0e3ec4,0xbf0ebec4,0x3f55bf6d,0xbf460000,0x3f22bf80,0xbf7f3f35,0xbdc9bf35,
0xbef13f7b,0xbf623e48,0x3e953f0e,0xbf753f55,0x3f75bec4,0xbe953f6d,0x3f62bf6d,0x3ef13ec4,0x3dc9bf55,0x3f7fbf0e,0xbf22be48,0x3f46bf7b,
0xbf353f80,0xbf358000,0xbf353f80,0xbf358000,0x3f350000,0xbf353f80,0x3f350000,0xbf353f80,0x3f35bf80,0x3f358000,0x3f35bf80,0x3f358000,
0xbf350000,0x3f35bf80,0xbf350000,0x3f35bf80,0x3f220000,0xbf463f80,0xbdc93f35,0xbf7f3f35,0x3f62bf7b,0x3ef13e48,0x3f75bf0e,0xbe953f55,
0xbe95bec4,0x3f75bf6d,0x3ef1bf6d,0x3f62bec4,0xbf7f3f55,0xbdc9bf0e,0xbf463e48,0x3f22bf7b,0x3f55bf80,0x3f0e8000,0x3f0e0000,0xbf553f80,
0xbe48bec4,0x3f7bbf6d,0x3f7bbf6d,0x3e483ec4,0xbf7b3f35,0x3e48bf35,0x3e48bf35,0x3f7bbf35,0xbf0e3f6d,0xbf553ec4,0xbf553ec4,0x3f0ebf6d,
0xbef10000,0x3f62bf80,0x3f75bf35,0xbe953f35,0xbf7f3f55,0x3dc9bf0e,0x3f46bf7b,0x3f22be48,0xbf223f6d,0xbf463ec4,0xbdc9bec4,0x3f7fbf6d,
0x3e953e48,0xbf753f7b,0xbf623f0e,0x3ef1bf55,0xbf6d3f80,0xbec48000,0x3f6dbf80,0x3ec48000,0xbec43f35,0xbf6d3f35,0x3ec4bf35,0x3f6dbf35,
0x3ec40000,0xbf6d3f80,0xbec40000,0x3f6dbf80,0x3f6dbf35,0xbec43f35,0xbf6d3f35,0x3ec4bf35,0x3e950000,0xbf753f80,0x3ef1bf35,0x3f62bf35,
0x3f46bf0e,0xbf223f55,0xbdc9be48,0x3f7fbf7b,0x3f7fbf6d,0xbdc93ec4,0xbf223ec4,0x3f46bf6d,0x3f62bf7b,0x3ef1be48,0xbf753f55,0x3e95bf0e,
0x3f7bbf80,0x3e488000,0xbe480000,0x3f7bbf80,0x3f55bf6d,0x3f0ebec4,0xbf0e3ec4,0x3f55bf6d,0x3f0ebf35,0x3f55bf35,0xbf553f35,0x3f0ebf35,
0x3e48bec4,0x3f7bbf6d,0xbf7b3f6d,0x3e48bec4,0xbdc90000,0x3f7fbf80,0xbf463f35,0x3f22bf35,0xbe953e48,0x3f75bf7b,0xbf623f55,0x3ef1bf0e,
0xbef13ec4,0x3f62bf6d,0xbf753f6d,0x3e95bec4,0xbf223f0e,0x3f46bf55,0xbf7f3f7b,0x3dc9be48,0x3f803f80,0xbf353f35,0x3f803f80,0xbf353f35,
0x3f803f80,0xbf353f35,0x3f803f80,0xbf353f35,0x3f803f80,0xbf353f35,0x3f803f80,0xbf353f35,0x3f803f80,0xbf353f35,0x3f803f80,0xbf353f35,
0x3f7e3f80,0xbdfbbcc9,0x3f1d3f31,0xbf4abf39,0x3f733f7a,0xbea1be60,0x3ee63f09,0xbf65bf58,0x3f5f3f6a,0xbefcbecf,0x3e893eb8,0xbf77bf6f,
0x3f423f51,0xbf27bf13,0x3d973e2f,0xbf7fbf7c,0x3f783f80,0xbe79bd49,0xbe79bd49,0xbf78bf80,0x3f4e3f67,0xbf18bedb,0xbf18bedb,0xbf4ebf67,
0x3f043f2c,0xbf5cbf3e,0xbf5cbf3e,0xbf04bf2c,0x3e163eac,0xbf7dbf71,0xbf7dbf71,0xbe16beac,0x3f6f3f7f,0xbeb8bd97,0xbf6abf42,0xbecfbf27,
0x3f133f4a,0xbf51bf1d,0xbf7cbf7e,0x3e2fbdfb,0x3cc93ea1,0xbf80bf73,0xbf39bf65,0x3f313ee6,0xbf09be89,0xbf58bf77,0xbe60befc,0x3f7a3f5f,
0x3f623f7f,0xbef1bdc9,0xbf62bf7f,0x3ef13dc9,0x3e953f22,0xbf75bf46,0xbe95bf22,0x3f753f46,0xbef1bdc9,0xbf62bf7f,0x3ef13dc9,0x3f623f7f,
0xbf75bf46,0xbe95bf22,0x3f753f46,0x3e953f22,0x3f513f7e,0xbf13bdfb,0xbe2fbf1d,0x3f7c3f4a,0xbcc93ee6,0xbf80bf65,0x3f393ea1,0x3f313f73,
0xbf58befc,0xbf09bf5f,0x3f7a3f77,0xbe603e89,0xbf6abf7f,0x3ecfbd97,0x3eb83f42,0xbf6fbf27,0x3f3e3f7d,0xbf2cbe16,0x3f2c3e16,0x3f3e3f7d,
0xbeac3e79,0xbf71bf78,0x3f713f78,0xbeac3e79,0xbf80bf4e,0xbd49bf18,0x3d493f18,0xbf80bf4e,0xbedbbf5c,0x3f673f04,0xbf67bf04,0xbedbbf5c,
0x3f273f7c,0xbf42be2f,0x3f7f3f51,0xbd973f13,0xbf1d3cc9,0xbf4abf80,0x3dfb3f39,0xbf7ebf31,0xbf65bf7a,0x3ee6be60,0xbf73bf09,0xbea1bf58,
0x3e89becf,0x3f773f6a,0xbefcbf6f,0x3f5f3eb8,0x3f0e3f7b,0xbf55be48,0x3f0e3f7b,0xbf55be48,0xbf55be48,0xbf0ebf7b,0xbf55be48,0xbf0ebf7b,
0xbf0ebf7b,0x3f553e48,0xbf0ebf7b,0x3f553e48,0x3f553e48,0x3f0e3f7b,0x3f553e48,0x3f0e3f7b,0x3ee63f7a,0xbf65be60,0xbea13f09,0xbf73bf58,
0xbf77becf,0xbe89bf6a,0xbf5fbf6f,0x3efcbeb8,0xbd97bf51,0x3f7f3f13,0x3f27be2f,0x3f423f7c,0x3f7e3f39,0xbdfb3f31,0x3f1d3f80,0xbf4abcc9,
0x3eac3f78,0xbf71be79,0xbf71be79,0xbeacbf78,0xbf80bf18,0x3d49bf4e,0x3d49bf4e,0x3f803f18,0x3edbbf04,0x3f673f5c,0x3f673f5c,0xbedb3f04,
0x3f2c3f7d,0xbf3e3e16,0xbf3e3e16,0xbf2cbf7d,0x3e603f77,0xbf7abe89,0xbf58bf5f,0x3f09befc,0xbf6fbf42,0x3eb8bf27,0x3f6a3d97,0x3ecf3f7f,
0x3f51bdfb,0x3f133f7e,0xbe2f3f4a,0xbf7cbf1d,0x3cc93f65,0xbf80bee6,0xbf39bf73,0x3f31bea1,0x3dc93f75,0xbf7fbe95,0xbdc9bf75,0x3f7f3e95,
0xbf46bf62,0x3f22bef1,0x3f463f62,0xbf223ef1,0x3f7f3e95,0x3dc93f75,0xbf7fbe95,0xbdc9bf75,0xbf223ef1,0xbf46bf62,0x3f22bef1,0x3f463f62,
0xbcc93f73,0xbf80bea1,0x3f39bee6,0x3f313f65,0xbf09bf77,0x3f58be89,0xbe603f5f,0xbf7abefc,0x3f6a3f27,0xbecf3f42,0xbeb8bf7f,0x3f6fbd97,
0xbf7cbdfb,0xbe2fbf7e,0x3f513f4a,0xbf133f1d,0xbe163f71,0xbf7dbeac,0x3f7d3eac,0xbe163f71,0xbe79bf80,0x3f78bd49,0xbf783d49,0xbe79bf80,
0x3f183f67,0xbf4e3edb,0x3f4ebedb,0x3f183f67,0xbf5cbf2c,0x3f04bf3e,0xbf043f3e,0xbf5cbf2c,0xbe893f6f,0xbf77beb8,0x3efc3f6a,0xbf5f3ecf,
0x3d97bf7c,0x3f7f3e2f,0xbf27bf51,0x3f42bf13,0x3dfb3f80,0xbf7e3cc9,0x3f4a3f31,0xbf1d3f39,0xbea1bf7a,0x3f73be60,0xbf65bf09,0x3ee6bf58,
0xbec43f6d,0xbf6dbec4,0xbec43f6d,0xbf6dbec4,0x3ec4bf6d,0x3f6d3ec4,0x3ec4bf6d,0x3f6d3ec4,0xbec43f6d,0xbf6dbec4,0xbec43f6d,0xbf6dbec4,
0x3ec4bf6d,0x3f6d3ec4,0x3ec4bf6d,0x3f6d3ec4,0xbefc3f6a,0xbf5fbecf,0xbf773eb8,0xbe89bf6f,0x3f27bf51,0x3f423f13,0x3f7fbe2f,0x3d973f7c,
0xbf4a3f31,0xbf1dbf39,0xbf7ebcc9,0x3dfbbf80,0x3f65bf09,0x3ee63f58,0x3f733e60,0xbea13f7a,0xbf183f67,0xbf4ebedb,0xbf4ebedb,0x3f18bf67,
0x3f5cbf2c,0x3f043f3e,0x3f043f3e,0xbf5c3f2c,0xbf7d3eac,0xbe16bf71,0xbe16bf71,0x3f7dbeac,0x3f783d49,0xbe793f80,0xbe793f80,0xbf78bd49,
0xbf313f65,0xbf39bee6,0xbcc9bf73,0x3f80bea1,0x3f7abefc,0x3e603f5f,0xbf093f77,0xbf58be89,0xbf6fbd97,0x3eb8bf7f,0x3f6abf27,0x3ecf3f42,
0x3f133f1d,0xbf513f4a,0xbf7c3dfb,0x3e2fbf7e,0xbf463f62,0xbf22bef1,0x3f46bf62,0x3f223ef1,0x3f7fbe95,0xbdc93f75,0xbf7f3e95,0x3dc9bf75,
0xbf22bef1,0x3f46bf62,0x3f223ef1,0xbf463f62,0xbdc93f75,0xbf7f3e95,0x3dc9bf75,0x3f7fbe95,0xbf583f5f,0xbf09befc,0x3f7abe89,0xbe603f77,
0x3f6abd97,0xbecf3f7f,0xbeb8bf27,0x3f6fbf42,0xbe2fbf4a,0x3f7cbf1d,0xbf133f7e,0xbf51bdfb,0xbf393f73,0xbf31bea1,0x3f80bee6,0xbcc93f65,
0xbf673f5c,0xbedbbf04,0x3edb3f04,0xbf673f5c,0x3f3e3e16,0xbf2c3f7d,0x3f2cbf7d,0x3f3e3e16,0x3eacbf78,0x3f71be79,0xbf713e79,0x3eacbf78,
0xbf803f18,0xbd49bf4e,0x3d493f4e,0xbf803f18,0xbf733f58,0xbea1bf09,0xbee63f7a,0xbf653e60,0x3efc3eb8,0xbf5f3f6f,0x3f77becf,0xbe893f6a,
0x3f42bf7c,0x3f273e2f,0x3d97bf51,0x3f7fbf13,0xbf4a3cc9,0x3f1dbf80,0xbf7e3f39,0xbdfbbf31,0xbf7b3f55,0xbe48bf0e,0xbf7b3f55,0xbe48bf0e,
0x3e483f0e,0xbf7b3f55,0x3e483f0e,0xbf7b3f55,0x3f7bbf55,0x3e483f0e,0x3f7bbf55,0x3e483f0e,0xbe48bf0e,0x3f7bbf55,0xbe48bf0e,0x3f7bbf55,
0xbf7f3f51,0xbd97bf13,0xbf423e2f,0x3f27bf7c,0xbdfb3f39,0xbf7e3f31,0xbf4a3f80,0xbf1dbcc9,0x3f73bf09,0xbea13f58,0x3ee63e60,0xbf653f7a,
0x3efcbf6f,0x3f5fbeb8,0x3f77bf6a,0x3e893ecf,0xbf803f4e,0x3d49bf18,0x3d49bf18,0x3f80bf4e,0xbedb3f5c,0xbf673f04,0xbf673f04,0x3edbbf5c,
0x3f2cbe16,0xbf3e3f7d,0xbf3e3f7d,0xbf2c3e16,0x3f71bf78,0x3eac3e79,0x3eac3e79,0xbf713f78,0xbf7c3f4a,0x3e2fbf1d,0x3f51bf7e,0x3f13bdfb,
0xbf313f73,0xbf393ea1,0xbcc9bee6,0x3f80bf65,0x3e603e89,0xbf7a3f77,0xbf583efc,0x3f09bf5f,0x3f6fbf27,0xbeb83f42,0xbf6a3f7f,0xbecfbd97,
0xbf753f46,0x3e95bf22,0x3f75bf46,0xbe953f22,0xbf623f7f,0xbef13dc9,0x3f62bf7f,0x3ef1bdc9,0xbe953f22,0xbf753f46,0x3e95bf22,0x3f75bf46,
0x3ef1bdc9,0xbf623f7f,0xbef13dc9,0x3f62bf7f,0xbf6a3f42,0x3ecfbf27,0x3eb8bd97,0xbf6f3f7f,0xbf7c3f7e,0xbe2fbdfb,0x3f51bf1d,0xbf133f4a,
0xbf393f65,0xbf313ee6,0x3f80bf73,0xbcc93ea1,0xbe603efc,0xbf7a3f5f,0x3f58bf77,0x3f09be89,0xbf5c3f3e,0x3f04bf2c,0xbf043f2c,0xbf5c3f3e,
0xbf7d3f71,0x3e16beac,0xbe163eac,0xbf7d3f71,0xbf783f80,0xbe793d49,0x3e79bd49,0xbf783f80,0xbf4e3f67,0xbf183edb,0x3f18bedb,0xbf4e3f67,
0xbf4a3f39,0x3f1dbf31,0xbf7e3f80,0xbdfb3cc9,0xbf653f58,0x3ee6bf09,0xbf733f7a,0xbea13e60,0xbf773f6f,0x3e89beb8,0xbf5f3f6a,0xbefc3ecf,
0xbf7f3f7c,0x3d97be2f,0xbf423f51,0xbf273f13,0x3f803f80,0xbf353f35,0x3f803f80,0xbf353f35,0x3f803f80,0xbf353f35,0x3f803f80,0xbf353f35,
0x3f803f80,0xbf353f35,0x3f803f80,0xbf353f35,0x3f803f80,0xbf353f35,0x3f803f80,0xbf353f35,0xbdfbbcc9,0xbf7ebf80,0xbf4abf39,0xbf1dbf31,
0xbea1be60,0xbf73bf7a,0xbf65bf58,0xbee6bf09,0xbefcbecf,0xbf5fbf6a,0xbf77bf6f,0xbe89beb8,0xbf27bf13,0xbf42bf51,0xbf7fbf7c,0xbd97be2f,
0xbf78bf80,0x3e793d49,0x3e793d49,0x3f783f80,0xbf4ebf67,0x3f183edb,0x3f183edb,0x3f4e3f67,0xbf04bf2c,0x3f5c3f3e,0x3f5c3f3e,0x3f043f2c,
0xbe16beac,0x3f7d3f71,0x3f7d3f71,0x3e163eac,0x3eb83d97,0x3f6f3f7f,0x3ecf3f27,0xbf6abf42,0x3f513f1d,0x3f133f4a,0xbe2f3dfb,0xbf7cbf7e,
0x3f803f73,0x3cc93ea1,0xbf31bee6,0xbf39bf65,0x3f583f77,0xbf09be89,0xbf7abf5f,0xbe60befc,0x3f623f7f,0xbef1bdc9,0xbf62bf7f,0x3ef13dc9,
0x3e953f22,0xbf75bf46,0xbe95bf22,0x3f753f46,0xbef1bdc9,0xbf62bf7f,0x3ef13dc9,0x3f623f7f,0xbf75bf46,0xbe95bf22,0x3f753f46,0x3e953f22,
0xbf13bdfb,0xbf51bf7e,0x3f7c3f4a,0x3e2f3f1d,0xbf80bf65,0x3cc9bee6,0x3f313f73,0xbf39bea1,0xbf09bf5f,0x3f583efc,0xbe603e89,0xbf7abf77,
0x3ecfbd97,0x3f6a3f7f,0xbf6fbf27,0xbeb8bf42,0xbf3ebf7d,0x3f2c3e16,0xbf2cbe16,0xbf3ebf7d,0x3eacbe79,0x3f713f78,0xbf71bf78,0x3eacbe79,
0x3f803f4e,0x3d493f18,0xbd49bf18,0x3f803f4e,0x3edb3f5c,0xbf67bf04,0x3f673f04,0x3edb3f5c,0x3f423e2f,0x3f273f7c,0x3d97bf13,0x3f7f3f51,
0x3f4a3f80,0xbf1d3cc9,0x3f7e3f31,0x3dfb3f39,0xbee63e60,0xbf65bf7a,0x3ea13f58,0xbf73bf09,0xbf77bf6a,0x3e89becf,0xbf5fbeb8,0xbefcbf6f,
0x3f0e3f7b,0xbf55be48,0x3f0e3f7b,0xbf55be48,0xbf55be48,0xbf0ebf7b,0xbf55be48,0xbf0ebf7b,0xbf0ebf7b,0x3f553e48,0xbf0ebf7b,0x3f553e48,
0x3f553e48,0x3f0e3f7b,0x3f553e48,0x3f0e3f7b,0xbf65be60,0xbee6bf7a,0xbf73bf58,0x3ea1bf09,0xbe89bf6a,0x3f773ecf,0x3efcbeb8,0x3f5f3f6f,
0x3f7f3f13,0x3d973f51,0x3f423f7c,0xbf273e2f,0xbdfb3f31,0xbf7ebf39,0xbf4abcc9,0xbf1dbf80,0xbeacbf78,0x3f713e79,0x3f713e79,0x3eac3f78,
0x3f803f18,0xbd493f4e,0xbd493f4e,0xbf80bf18,0xbedb3f04,0xbf67bf5c,0xbf67bf5c,0x3edbbf04,0xbf2cbf7d,0x3f3ebe16,0x3f3ebe16,0x3f2c3f7d,
0x3f7a3e89,0x3e603f77,0xbf093efc,0xbf58bf5f,0xbeb83f27,0xbf6fbf42,0xbecfbf7f,0x3f6a3d97,0xbf13bf7e,0x3f51bdfb,0x3f7c3f1d,0xbe2f3f4a,
0x3f803ee6,0x3cc93f65,0xbf313ea1,0xbf39bf73,0x3dc93f75,0xbf7fbe95,0xbdc9bf75,0x3f7f3e95,0xbf46bf62,0x3f22bef1,0x3f463f62,0xbf223ef1,
0x3f7f3e95,0x3dc93f75,0xbf7fbe95,0xbdc9bf75,0xbf223ef1,0xbf46bf62,0x3f22bef1,0x3f463f62,0xbf80bea1,0x3cc9bf73,0x3f313f65,0xbf393ee6,
0x3f58be89,0x3f093f77,0xbf7abefc,0x3e60bf5f,0xbecf3f42,0xbf6abf27,0x3f6fbd97,0x3eb83f7f,0xbe2fbf7e,0x3f7c3dfb,0xbf133f1d,0xbf51bf4a,
0x3e16bf71,0x3f7d3eac,0xbf7dbeac,0x3e16bf71,0x3e793f80,0xbf783d49,0x3f78bd49,0x3e793f80,0xbf18bf67,0x3f4ebedb,0xbf4e3edb,0xbf18bf67,
0x3f5c3f2c,0xbf043f3e,0x3f04bf3e,0x3f5c3f2c,0x3f773eb8,0xbe893f6f,0x3f5fbecf,0x3efc3f6a,0xbf7fbe2f,0x3d97bf7c,0xbf423f13,0xbf27bf51,
0x3f7ebcc9,0x3dfb3f80,0x3f1dbf39,0x3f4a3f31,0xbf733e60,0xbea1bf7a,0xbee63f58,0xbf65bf09,0xbec43f6d,0xbf6dbec4,0xbec43f6d,0xbf6dbec4,
0x3ec4bf6d,0x3f6d3ec4,0x3ec4bf6d,0x3f6d3ec4,0xbec43f6d,0xbf6dbec4,0xbec43f6d,0xbf6dbec4,0x3ec4bf6d,0x3f6d3ec4,0x3ec4bf6d,0x3f6d3ec4,
0xbf5fbecf,0x3efcbf6a,0xbe89bf6f,0x3f77beb8,0x3f423f13,0xbf273f51,0x3d973f7c,0xbf7f3e2f,0xbf1dbf39,0x3f4abf31,0x3dfbbf80,0x3f7e3cc9,
0x3ee63f58,0xbf653f09,0xbea13f7a,0xbf73be60,0x3f18bf67,0x3f4e3edb,0x3f4e3edb,0xbf183f67,0xbf5c3f2c,0xbf04bf3e,0xbf04bf3e,0x3f5cbf2c,
0x3f7dbeac,0x3e163f71,0x3e163f71,0xbf7d3eac,0xbf78bd49,0x3e79bf80,0x3e79bf80,0x3f783d49,0x3f393ee6,0xbf313f65,0xbf803ea1,0xbcc9bf73,
0xbe60bf5f,0x3f7abefc,0x3f583e89,0xbf093f77,0xbeb83f7f,0xbf6fbd97,0xbecfbf42,0x3f6abf27,0x3f51bf4a,0x3f133f1d,0xbe2f3f7e,0xbf7c3dfb,
0xbf463f62,0xbf22bef1,0x3f46bf62,0x3f223ef1,0x3f7fbe95,0xbdc93f75,0xbf7f3e95,0x3dc9bf75,0xbf22bef1,0x3f46bf62,0x3f223ef1,0xbf463f62,
0xbdc93f75,0xbf7f3e95,0x3dc9bf75,0x3f7fbe95,0xbf09befc,0x3f58bf5f,0xbe603f77,0xbf7a3e89,0xbecf3f7f,0xbf6a3d97,0x3f6fbf42,0x3eb83f27,
0x3f7cbf1d,0x3e2f3f4a,0xbf51bdfb,0x3f13bf7e,0xbf31bea1,0x3f39bf73,0xbcc93f65,0xbf803ee6,0x3f67bf5c,0x3edb3f04,0xbedbbf04,0x3f67bf5c,
0xbf3ebe16,0x3f2cbf7d,0xbf2c3f7d,0xbf3ebe16,0xbeac3f78,0xbf713e79,0x3f71be79,0xbeac3f78,0x3f80bf18,0x3d493f4e,0xbd49bf4e,0x3f80bf18,
0x3ea13f09,0xbf733f58,0x3f65be60,0xbee63f7a,0x3f5fbf6f,0x3efc3eb8,0x3e89bf6a,0x3f77becf,0xbf27be2f,0x3f42bf7c,0xbf7f3f13,0x3d97bf51,
0xbf1d3f80,0xbf4a3cc9,0x3dfb3f31,0xbf7e3f39,0xbf7b3f55,0xbe48bf0e,0xbf7b3f55,0xbe48bf0e,0x3e483f0e,0xbf7b3f55,0x3e483f0e,0xbf7b3f55,
0x3f7bbf55,0x3e483f0e,0x3f7bbf55,0x3e483f0e,0xbe48bf0e,0x3f7bbf55,0xbe48bf0e,0x3f7bbf55,0xbd97bf13,0x3f7fbf51,0x3f27bf7c,0x3f42be2f,
0xbf7e3f31,0x3dfbbf39,0xbf1dbcc9,0x3f4abf80,0xbea13f58,0xbf733f09,0xbf653f7a,0xbee6be60,0x3f5fbeb8,0xbefc3f6f,0x3e893ecf,0xbf773f6a,
0x3f80bf4e,0xbd493f18,0xbd493f18,0xbf803f4e,0x3edbbf5c,0x3f67bf04,0x3f67bf04,0xbedb3f5c,0xbf2c3e16,0x3f3ebf7d,0x3f3ebf7d,0x3f2cbe16,
0xbf713f78,0xbeacbe79,0xbeacbe79,0x3f71bf78,0xbe2f3f1d,0xbf7c3f4a,0xbf133dfb,0x3f51bf7e,0x3f39bea1,0xbf313f73,0xbf803f65,0xbcc9bee6,
0x3f7abf77,0x3e603e89,0xbf093f5f,0xbf583efc,0x3eb8bf42,0x3f6fbf27,0x3ecf3d97,0xbf6a3f7f,0xbf753f46,0x3e95bf22,0x3f75bf46,0xbe953f22,
0xbf623f7f,0xbef13dc9,0x3f62bf7f,0x3ef1bdc9,0xbe953f22,0xbf753f46,0x3e95bf22,0x3f75bf46,0x3ef1bdc9,0xbf623f7f,0xbef13dc9,0x3f62bf7f,
0x3ecfbf27,0x3f6abf42,0xbf6f3f7f,0xbeb83d97,0xbe2fbdfb,0x3f7cbf7e,0xbf133f4a,0xbf513f1d,0xbf313ee6,0x3f39bf65,0xbcc93ea1,0xbf803f73,
0xbf7a3f5f,0x3e60befc,0x3f09be89,0xbf583f77,0x3f5cbf3e,0xbf043f2c,0x3f04bf2c,0x3f5cbf3e,0x3f7dbf71,0xbe163eac,0x3e16beac,0x3f7dbf71,
0x3f78bf80,0x3e79bd49,0xbe793d49,0x3f78bf80,0x3f4ebf67,0x3f18bedb,0xbf183edb,0x3f4ebf67,0xbf1d3f31,0xbf4a3f39,0x3dfbbcc9,0xbf7e3f80,
0xbee63f09,0xbf653f58,0x3ea1be60,0xbf733f7a,0xbe893eb8,0xbf773f6f,0x3efcbecf,0xbf5f3f6a,0xbd973e2f,0xbf7f3f7c,0x3f27bf13,0xbf423f51,
0x3f803f80,0xbf353f35,0x3f803f80,0xbf353f35,0x3f803f80,0xbf353f35,0x3f803f80,0xbf353f35,0x3f803f80,0xbf353f35,0x3f803f80,0xbf353f35,
0x3f803f80,0xbf353f35,0x3f803f80,0xbf353f35,0xbf7ebf80,0x3dfb3cc9,0xbf1dbf31,0x3f4a3f39,0xbf73bf7a,0x3ea13e60,0xbee6bf09,0x3f653f58,
0xbf5fbf6a,0x3efc3ecf,0xbe89beb8,0x3f773f6f,0xbf42bf51,0x3f273f13,0xbd97be2f,0x3f7f3f7c,0x3f783f80,0xbe79bd49,0xbe79bd49,0xbf78bf80,
0x3f4e3f67,0xbf18bedb,0xbf18bedb,0xbf4ebf67,0x3f043f2c,0xbf5cbf3e,0xbf5cbf3e,0xbf04bf2c,0x3e163eac,0xbf7dbf71,0xbf7dbf71,0xbe16beac,
0xbf6fbf7f,0x3eb83d97,0x3f6a3f42,0x3ecf3f27,0xbf13bf4a,0x3f513f1d,0x3f7c3f7e,0xbe2f3dfb,0xbcc9bea1,0x3f803f73,0x3f393f65,0xbf31bee6,
0x3f093e89,0x3f583f77,0x3e603efc,0xbf7abf5f,0x3f623f7f,0xbef1bdc9,0xbf62bf7f,0x3ef13dc9,0x3e953f22,0xbf75bf46,0xbe95bf22,0x3f753f46,
0xbef1bdc9,0xbf62bf7f,0x3ef13dc9,0x3f623f7f,0xbf75bf46,0xbe95bf22,0x3f753f46,0x3e953f22,0xbf51bf7e,0x3f133dfb,0x3e2f3f1d,0xbf7cbf4a,
0x3cc9bee6,0x3f803f65,0xbf39bea1,0xbf31bf73,0x3f583efc,0x3f093f5f,0xbf7abf77,0x3e60be89,0x3f6a3f7f,0xbecf3d97,0xbeb8bf42,0x3f6f3f27,
0x3f3e3f7d,0xbf2cbe16,0x3f2c3e16,0x3f3e3f7d,0xbeac3e79,0xbf71bf78,0x3f713f78,0xbeac3e79,0xbf80bf4e,0xbd49bf18,0x3d493f18,0xbf80bf4e,
0xbedbbf5c,0x3f673f04,0xbf67bf04,0xbedbbf5c,0xbf27bf7c,0x3f423e2f,0xbf7fbf51,0x3d97bf13,0x3f1dbcc9,0x3f4a3f80,0xbdfbbf39,0x3f7e3f31,
0x3f653f7a,0xbee63e60,0x3f733f09,0x3ea13f58,0xbe893ecf,0xbf77bf6a,0x3efc3f6f,0xbf5fbeb8,0x3f0e3f7b,0xbf55be48,0x3f0e3f7b,0xbf55be48,
0xbf55be48,0xbf0ebf7b,0xbf55be48,0xbf0ebf7b,0xbf0ebf7b,0x3f553e48,0xbf0ebf7b,0x3f553e48,0x3f553e48,0x3f0e3f7b,0x3f553e48,0x3f0e3f7b,
0xbee6bf7a,0x3f653e60,0x3ea1bf09,0x3f733f58,0x3f773ecf,0x3e893f6a,0x3f5f3f6f,0xbefc3eb8,0x3d973f51,0xbf7fbf13,0xbf273e2f,0xbf42bf7c,
0xbf7ebf39,0x3dfbbf31,0xbf1dbf80,0x3f4a3cc9,0x3eac3f78,0xbf71be79,0xbf71be79,0xbeacbf78,0xbf80bf18,0x3d49bf4e,0x3d49bf4e,0x3f803f18,
0x3edbbf04,0x3f673f5c,0x3f673f5c,0xbedb3f04,0x3f2c3f7d,0xbf3e3e16,0xbf3e3e16,0xbf2cbf7d,0xbe60bf77,0x3f7a3e89,0x3f583f5f,0xbf093efc,
0x3f6f3f42,0xbeb83f27,0xbf6abd97,0xbecfbf7f,0xbf513dfb,0xbf13bf7e,0x3e2fbf4a,0x3f7c3f1d,0xbcc9bf65,0x3f803ee6,0x3f393f73,0xbf313ea1,
0x3dc93f75,0xbf7fbe95,0xbdc9bf75,0x3f7f3e95,0xbf46bf62,0x3f22bef1,0x3f463f62,0xbf223ef1,0x3f7f3e95,0x3dc93f75,0xbf7fbe95,0xbdc9bf75,
0xbf223ef1,0xbf46bf62,0x3f22bef1,0x3f463f62,0x3cc9bf73,0x3f803ea1,0xbf393ee6,0xbf31bf65,0x3f093f77,0xbf583e89,0x3e60bf5f,0x3f7a3efc,
0xbf6abf27,0x3ecfbf42,0x3eb83f7f,0xbf6f3d97,0x3f7c3dfb,0x3e2f3f7e,0xbf51bf4a,0x3f13bf1d,0xbe163f71,0xbf7dbeac,0x3f7d3eac,0xbe163f71,
0xbe79bf80,0x3f78bd49,0xbf783d49,0xbe79bf80,0x3f183f67,0xbf4e3edb,0x3f4ebedb,0x3f183f67,0xbf5cbf2c,0x3f04bf3e,0xbf043f3e,0xbf5cbf2c,
0x3e89bf6f,0x3f773eb8,0xbefcbf6a,0x3f5fbecf,0xbd973f7c,0xbf7fbe2f,0x3f273f51,0xbf423f13,0xbdfbbf80,0x3f7ebcc9,0xbf4abf31,0x3f1dbf39,
0x3ea13f7a,0xbf733e60,0x3f653f09,0xbee63f58,0xbec43f6d,0xbf6dbec4,0xbec43f6d,0xbf6dbec4,0x3ec4bf6d,0x3f6d3ec4,0x3ec4bf6d,0x3f6d3ec4,
0xbec43f6d,0xbf6dbec4,0xbec43f6d,0xbf6dbec4,0x3ec4bf6d,0x3f6d3ec4,0x3ec4bf6d,0x3f6d3ec4,0x3efcbf6a,0x3f5f3ecf,0x3f77beb8,0x3e893f6f,
0xbf273f51,0xbf42bf13,0xbf7f3e2f,0xbd97bf7c,0x3f4abf31,0x3f1d3f39,0x3f7e3cc9,0xbdfb3f80,0xbf653f09,0xbee6bf58,0xbf73be60,0x3ea1bf7a,
0xbf183f67,0xbf4ebedb,0xbf4ebedb,0x3f18bf67,0x3f5cbf2c,0x3f043f3e,0x3f043f3e,0xbf5c3f2c,0xbf7d3eac,0xbe16bf71,0xbe16bf71,0x3f7dbeac,
0x3f783d49,0xbe793f80,0xbe793f80,0xbf78bd49,0x3f31bf65,0x3f393ee6,0x3cc93f73,0xbf803ea1,0xbf7a3efc,0xbe60bf5f,0x3f09bf77,0x3f583e89,
0x3f6f3d97,0xbeb83f7f,0xbf6a3f27,0xbecfbf42,0xbf13bf1d,0x3f51bf4a,0x3f7cbdfb,0xbe2f3f7e,0xbf463f62,0xbf22bef1,0x3f46bf62,0x3f223ef1,
0x3f7fbe95,0xbdc93f75,0xbf7f3e95,0x3dc9bf75,0xbf22bef1,0x3f46bf62,0x3f223ef1,0xbf463f62,0xbdc93f75,0xbf7f3e95,0x3dc9bf75,0x3f7fbe95,
0x3f58bf5f,0x3f093efc,0xbf7a3e89,0x3e60bf77,0xbf6a3d97,0x3ecfbf7f,0x3eb83f27,0xbf6f3f42,0x3e2f3f4a,0xbf7c3f1d,0x3f13bf7e,0x3f513dfb,
0x3f39bf73,0x3f313ea1,0xbf803ee6,0x3cc9bf65,0xbf673f5c,0xbedbbf04,0x3edb3f04,0xbf673f5c,0x3f3e3e16,0xbf2c3f7d,0x3f2cbf7d,0x3f3e3e16,
0x3eacbf78,0x3f71be79,0xbf713e79,0x3eacbf78,0xbf803f18,0xbd49bf4e,0x3d493f4e,0xbf803f18,0x3f73bf58,0x3ea13f09,0x3ee6bf7a,0x3f65be60,
0xbefcbeb8,0x3f5fbf6f,0xbf773ecf,0x3e89bf6a,0xbf423f7c,0xbf27be2f,0xbd973f51,0xbf7f3f13,0x3f4abcc9,0xbf1d3f80,0x3f7ebf39,0x3dfb3f31,
0xbf7b3f55,0xbe48bf0e,0xbf7b3f55,0xbe48bf0e,0x3e483f0e,0xbf7b3f55,0x3e483f0e,0xbf7b3f55,0x3f7bbf55,0x3e483f0e,0x3f7bbf55,0x3e483f0e,
0xbe48bf0e,0x3f7bbf55,0xbe48bf0e,0x3f7bbf55,0x3f7fbf51,0x3d973f13,0x3f42be2f,0xbf273f7c,0x3dfbbf39,0x3f7ebf31,0x3f4abf80,0x3f1d3cc9,
0xbf733f09,0x3ea1bf58,0xbee6be60,0x3f65bf7a,0xbefc3f6f,0xbf5f3eb8,0xbf773f6a,0xbe89becf,0xbf803f4e,0x3d49bf18,0x3d49bf18,0x3f80bf4e,
0xbedb3f5c,0xbf673f04,0xbf673f04,0x3edbbf5c,0x3f2cbe16,0xbf3e3f7d,0xbf3e3f7d,0xbf2c3e16,0x3f71bf78,0x3eac3e79,0x3eac3e79,0xbf713f78,
0x3f7cbf4a,0xbe2f3f1d,0xbf513f7e,0xbf133dfb,0x3f31bf73,0x3f39bea1,0x3cc93ee6,0xbf803f65,0xbe60be89,0x3f7abf77,0x3f58befc,0xbf093f5f,
0xbf6f3f27,0x3eb8bf42,0x3f6abf7f,0x3ecf3d97,0xbf753f46,0x3e95bf22,0x3f75bf46,0xbe953f22,0xbf623f7f,0xbef13dc9,0x3f62bf7f,0x3ef1bdc9,
0xbe953f22,0xbf753f46,0x3e95bf22,0x3f75bf46,0x3ef1bdc9,0xbf623f7f,0xbef13dc9,0x3f62bf7f,0x3f6abf42,0xbecf3f27,0xbeb83d97,0x3f6fbf7f,
0x3f7cbf7e,0x3e2f3dfb,0xbf513f1d,0x3f13bf4a,0x3f39bf65,0x3f31bee6,0xbf803f73,0x3cc9bea1,0x3e60befc,0x3f7abf5f,0xbf583f77,0xbf093e89,
0xbf5c3f3e,0x3f04bf2c,0xbf043f2c,0xbf5c3f3e,0xbf7d3f71,0x3e16beac,0xbe163eac,0xbf7d3f71,0xbf783f80,0xbe793d49,0x3e79bd49,0xbf783f80,
0xbf4e3f67,0xbf183edb,0x3f18bedb,0xbf4e3f67,0x3f4abf39,0xbf1d3f31,0x3f7ebf80,0x3dfbbcc9,0x3f65bf58,0xbee63f09,0x3f73bf7a,0x3ea1be60,
0x3f77bf6f,0xbe893eb8,0x3f5fbf6a,0x3efcbecf,0x3f7fbf7c,0xbd973e2f,0x3f42bf51,0x3f27bf13,0x3f803f80,0xbf353f35,0x3f803f80,0xbf353f35,
0x3f803f80,0xbf353f35,0x3f803f80,0xbf353f35,0x3f803f80,0xbf353f35,0x3f803f80,0xbf353f35,0x3f803f80,0xbf353f35,0x3f803f80,0xbf353f35,
0x3dfb3cc9,0x3f7e3f80,0x3f4a3f39,0x3f1d3f31,0x3ea13e60,0x3f733f7a,0x3f653f58,0x3ee63f09,0x3efc3ecf,0x3f5f3f6a,0x3f773f6f,0x3e893eb8,
0x3f273f13,0x3f423f51,0x3f7f3f7c,0x3d973e2f,0xbf78bf80,0x3e793d49,0x3e793d49,0x3f783f80,0xbf4ebf67,0x3f183edb,0x3f183edb,0x3f4e3f67,
0xbf04bf2c,0x3f5c3f3e,0x3f5c3f3e,0x3f043f2c,0xbe16beac,0x3f7d3f71,0x3f7d3f71,0x3e163eac,0xbeb8bd97,0xbf6fbf7f,0xbecfbf27,0x3f6a3f42,
0xbf51bf1d,0xbf13bf4a,0x3e2fbdfb,0x3f7c3f7e,0xbf80bf73,0xbcc9bea1,0x3f313ee6,0x3f393f65,0xbf58bf77,0x3f093e89,0x3f7a3f5f,0x3e603efc,
0x3f623f7f,0xbef1bdc9,0xbf62bf7f,0x3ef13dc9,0x3e953f22,0xbf75bf46,0xbe95bf22,0x3f753f46,0xbef1bdc9,0xbf62bf7f,0x3ef13dc9,0x3f623f7f,
0xbf75bf46,0xbe95bf22,0x3f753f46,0x3e953f22,0x3f133dfb,0x3f513f7e,0xbf7cbf4a,0xbe2fbf1d,0x3f803f65,0xbcc93ee6,0xbf31bf73,0x3f393ea1,
0x3f093f5f,0xbf58befc,0x3e60be89,0x3f7a3f77,0xbecf3d97,0xbf6abf7f,0x3f6f3f27,0x3eb83f42,0xbf3ebf7d,0x3f2c3e16,0xbf2cbe16,0xbf3ebf7d,
0x3eacbe79,0x3f713f78,0xbf71bf78,0x3eacbe79,0x3f803f4e,0x3d493f18,0xbd49bf18,0x3f803f4e,0x3edb3f5c,0xbf67bf04,0x3f673f04,0x3edb3f5c,
0xbf42be2f,0xbf27bf7c,0xbd973f13,0xbf7fbf51,0xbf4abf80,0x3f1dbcc9,0xbf7ebf31,0xbdfbbf39,0x3ee6be60,0x3f653f7a,0xbea1bf58,0x3f733f09,
0x3f773f6a,0xbe893ecf,0x3f5f3eb8,0x3efc3f6f,0x3f0e3f7b,0xbf55be48,0x3f0e3f7b,0xbf55be48,0xbf55be48,0xbf0ebf7b,0xbf55be48,0xbf0ebf7b,
0xbf0ebf7b,0x3f553e48,0xbf0ebf7b,0x3f553e48,0x3f553e48,0x3f0e3f7b,0x3f553e48,0x3f0e3f7b,0x3f653e60,0x3ee63f7a,0x3f733f58,0xbea13f09,
0x3e893f6a,0xbf77becf,0xbefc3eb8,0xbf5fbf6f,0xbf7fbf13,0xbd97bf51,0xbf42bf7c,0x3f27be2f,0x3dfbbf31,0x3f7e3f39,0x3f4a3cc9,0x3f1d3f80,
0xbeacbf78,0x3f713e79,0x3f713e79,0x3eac3f78,0x3f803f18,0xbd493f4e,0xbd493f4e,0xbf80bf18,0xbedb3f04,0xbf67bf5c,0xbf67bf5c,0x3edbbf04,
0xbf2cbf7d,0x3f3ebe16,0x3f3ebe16,0x3f2c3f7d,0xbf7abe89,0xbe60bf77,0x3f09befc,0x3f583f5f,0x3eb8bf27,0x3f6f3f42,0x3ecf3f7f,0xbf6abd97,
0x3f133f7e,0xbf513dfb,0xbf7cbf1d,0x3e2fbf4a,0xbf80bee6,0xbcc9bf65,0x3f31bea1,0x3f393f73,0x3dc93f75,0xbf7fbe95,0xbdc9bf75,0x3f7f3e95,
0xbf46bf62,0x3f22bef1,0x3f463f62,0xbf223ef1,0x3f7f3e95,0x3dc93f75,0xbf7fbe95,0xbdc9bf75,0xbf223ef1,0xbf46bf62,0x3f22bef1,0x3f463f62,
0x3f803ea1,0xbcc93f73,0xbf31bf65,0x3f39bee6,0xbf583e89,0xbf09bf77,0x3f7a3efc,0xbe603f5f,0x3ecfbf42,0x3f6a3f27,0xbf6f3d97,0xbeb8bf7f,
0x3e2f3f7e,0xbf7cbdfb,0x3f13bf1d,0x3f513f4a,0x3e16bf71,0x3f7d3eac,0xbf7dbeac,0x3e16bf71,0x3e793f80,0xbf783d49,0x3f78bd49,0x3e793f80,
0xbf18bf67,0x3f4ebedb,0xbf4e3edb,0xbf18bf67,0x3f5c3f2c,0xbf043f3e,0x3f04bf3e,0x3f5c3f2c,0xbf77beb8,0x3e89bf6f,0xbf5f3ecf,0xbefcbf6a,
0x3f7f3e2f,0xbd973f7c,0x3f42bf13,0x3f273f51,0xbf7e3cc9,0xbdfbbf80,0xbf1d3f39,0xbf4abf31,0x3f73be60,0x3ea13f7a,0x3ee6bf58,0x3f653f09,
0xbec43f6d,0xbf6dbec4,0xbec43f6d,0xbf6dbec4,0x3ec4bf6d,0x3f6d3ec4,0x3ec4bf6d,0x3f6d3ec4,0xbec43f6d,0xbf6dbec4,0xbec43f6d,0xbf6dbec4,
0x3ec4bf6d,0x3f6d3ec4,0x3ec4bf6d,0x3f6d3ec4,0x3f5f3ecf,0xbefc3f6a,0x3e893f6f,0xbf773eb8,0xbf42bf13,0x3f27bf51,0xbd97bf7c,0x3f7fbe2f,
0x3f1d3f39,0xbf4a3f31,0xbdfb3f80,0xbf7ebcc9,0xbee6bf58,0x3f65bf09,0x3ea1bf7a,0x3f733e60,0x3f18bf67,0x3f4e3edb,0x3f4e3edb,0xbf183f67,
0xbf5c3f2c,0xbf04bf3e,0xbf04bf3e,0x3f5cbf2c,0x3f7dbeac,0x3e163f71,0x3e163f71,0xbf7d3eac,0xbf78bd49,0x3e79bf80,0x3e79bf80,0x3f783d49,
0xbf39bee6,0x3f31bf65,0x3f80bea1,0x3cc93f73,0x3e603f5f,0xbf7a3efc,0xbf58be89,0x3f09bf77,0x3eb8bf7f,0x3f6f3d97,0x3ecf3f42,0xbf6a3f27,
0xbf513f4a,0xbf13bf1d,0x3e2fbf7e,0x3f7cbdfb,0xbf463f62,0xbf22bef1,0x3f46bf62,0x3f223ef1,0x3f7fbe95,0xbdc93f75,0xbf7f3e95,0x3dc9bf75,
0xbf22bef1,0x3f46bf62,0x3f223ef1,0xbf463f62,0xbdc93f75,0xbf7f3e95,0x3dc9bf75,0x3f7fbe95,0x3f093efc,0xbf583f5f,0x3e60bf77,0x3f7abe89,
0x3ecfbf7f,0x3f6abd97,0xbf6f3f42,0xbeb8bf27,0xbf7c3f1d,0xbe2fbf4a,0x3f513dfb,0xbf133f7e,0x3f313ea1,0xbf393f73,0x3cc9bf65,0x3f80bee6,
0x3f67bf5c,0x3edb3f04,0xbedbbf04,0x3f67bf5c,0xbf3ebe16,0x3f2cbf7d,0xbf2c3f7d,0xbf3ebe16,0xbeac3f78,0xbf713e79,0x3f71be79,0xbeac3f78,
0x3f80bf18,0x3d493f4e,0xbd49bf4e,0x3f80bf18,0xbea1bf09,0x3f73bf58,0xbf653e60,0x3ee6bf7a,0xbf5f3f6f,0xbefcbeb8,0xbe893f6a,0xbf773ecf,
0x3f273e2f,0xbf423f7c,0x3f7fbf13,0xbd973f51,0x3f1dbf80,0x3f4abcc9,0xbdfbbf31,0x3f7ebf39,0xbf7b3f55,0xbe48bf0e,0xbf7b3f55,0xbe48bf0e,
0x3e483f0e,0xbf7b3f55,0x3e483f0e,0xbf7b3f55,0x3f7bbf55,0x3e483f0e,0x3f7bbf55,0x3e483f0e,0xbe48bf0e,0x3f7bbf55,0xbe48bf0e,0x3f7bbf55,
0x3d973f13,0xbf7f3f51,0xbf273f7c,0xbf423e2f,0x3f7ebf31,0xbdfb3f39,0x3f1d3cc9,0xbf4a3f80,0x3ea1bf58,0x3f73bf09,0x3f65bf7a,0x3ee63e60,
0xbf5f3eb8,0x3efcbf6f,0xbe89becf,0x3f77bf6a,0x3f80bf4e,0xbd493f18,0xbd493f18,0xbf803f4e,0x3edbbf5c,0x3f67bf04,0x3f67bf04,0xbedb3f5c,
0xbf2c3e16,0x3f3ebf7d,0x3f3ebf7d,0x3f2cbe16,0xbf713f78,0xbeacbe79,0xbeacbe79,0x3f71bf78,0x3e2fbf1d,0x3f7cbf4a,0x3f13bdfb,0xbf513f7e,
0xbf393ea1,0x3f31bf73,0x3f80bf65,0x3cc93ee6,0xbf7a3f77,0xbe60be89,0x3f09bf5f,0x3f58befc,0xbeb83f42,0xbf6f3f27,0xbecfbd97,0x3f6abf7f,
0xbf753f46,0x3e95bf22,0x3f75bf46,0xbe953f22,0xbf623f7f,0xbef13dc9,0x3f62bf7f,0x3ef1bdc9,0xbe953f22,0xbf753f46,0x3e95bf22,0x3f75bf46,
0x3ef1bdc9,0xbf623f7f,0xbef13dc9,0x3f62bf7f,0xbecf3f27,0xbf6a3f42,0x3f6fbf7f,0x3eb8bd97,0x3e2f3dfb,0xbf7c3f7e,0x3f13bf4a,0x3f51bf1d,
0x3f31bee6,0xbf393f65,0x3cc9bea1,0x3f80bf73,0x3f7abf5f,0xbe603efc,0xbf093e89,0x3f58bf77,0x3f5cbf3e,0xbf043f2c,0x3f04bf2c,0x3f5cbf3e,
0x3f7dbf71,0xbe163eac,0x3e16beac,0x3f7dbf71,0x3f78bf80,0x3e79bd49,0xbe793d49,0x3f78bf80,0x3f4ebf67,0x3f18bedb,0xbf183edb,0x3f4ebf67,
0x3f1dbf31,0x3f4abf39,0xbdfb3cc9,0x3f7ebf80,0x3ee6bf09,0x3f65bf58,0xbea13e60,0x3f73bf7a,0x3e89beb8,0x3f77bf6f,0xbefc3ecf,0x3f5fbf6a,
0x3d97be2f,0x3f7fbf7c,0xbf273f13,0x3f42bf51,0x3f803f80,0xbf803f80,0x3f803f80,0xbf803f80,0x3f803f80,0xbf803f80,0x3f803f80,0xbf803f80,
0x3f803f80,0xbf803f80,0x3f803f80,0xbf803f80,0x3f803f80,0xbf803f80,0x3f803f80,0xbf803f80,0x3f7d3f80,0xbe16bd49,0x3f183f2c,0xbf4ebf3e,
0x3f713f78,0xbeacbe79,0x3edb3f04,0xbf67bf5c,0x3f5c3f67,0xbf04bedb,0x3e793eac,0xbf78bf71,0x3f3e3f4e,0xbf2cbf18,0x3d493e16,0xbf80bf7d,
0x3f753f7f,0xbe95bdc9,0xbe95bdc9,0xbf75bf7f,0x3f463f62,0xbf22bef1,0xbf22bef1,0xbf46bf62,0x3ef13f22,0xbf62bf46,0xbf62bf46,0xbef1bf22,
0x3dc93e95,0xbf7fbf75,0xbf7fbf75,0xbdc9be95,0x3f673f7d,0xbedbbe16,0xbf71bf4e,0xbeacbf18,0x3f043f3e,0xbf5cbf2c,0xbf78bf80,0x3e79bd49,
0xbd493e79,0xbf80bf78,0xbf2cbf5c,0x3f3e3f04,0xbf18beac,0xbf4ebf71,0xbe16bedb,0x3f7d3f67,0x3f553f7b,0xbf0ebe48,0xbf55bf7b,0x3f0e3e48,
0x3e483f0e,0xbf7bbf55,0xbe48bf0e,0x3f7b3f55,0xbf0ebe48,0xbf55bf7b,0x3f0e3e48,0x3f553f7b,0xbf7bbf55,0xbe48bf0e,0x3f7b3f55,0x3e483f0e,
0x3f3e3f78,0xbf2cbe79,0xbd49bf04,0x3f803f5c,0xbe163eac,0xbf7dbf71,0x3f4e3edb,0x3f183f67,0xbf67bf18,0xbedbbf4e,0x3f713f7d,0xbeac3e16,
0xbf5cbf80,0x3f043d49,0x3e793f2c,0xbf78bf3e,0x3f223f75,0xbf46be95,0x3f463e95,0x3f223f75,0xbef13dc9,0xbf62bf7f,0x3f623f7f,0xbef13dc9,
0xbf7fbf62,0x3dc9bef1,0xbdc93ef1,0xbf7fbf62,0xbe95bf46,0x3f753f22,0xbf75bf22,0xbe95bf46,0x3f043f71,0xbf5cbeac,0x3f783f67,0xbe793edb,
0xbf3ebe16,0xbf2cbf7d,0xbd493f18,0xbf80bf4e,0xbf4ebf80,0x3f18bd49,0xbf7dbf2c,0xbe16bf3e,0x3edbbe79,0x3f673f78,0xbeacbf5c,0x3f713f04,
0x3ec43f6d,0xbf6dbec4,0x3ec43f6d,0xbf6dbec4,0xbf6dbec4,0xbec4bf6d,0xbf6dbec4,0xbec4bf6d,0xbec4bf6d,0x3f6d3ec4,0xbec4bf6d,0x3f6d3ec4,
0x3f6d3ec4,0x3ec43f6d,0x3f6d3ec4,0x3ec43f6d,0x3e793f67,0xbf78bedb,0xbf043eac,0xbf5cbf71,0xbf80bf18,0xbd49bf4e,0xbf3ebf7d,0x3f2cbe16,
0x3e16bf2c,0x3f7d3f3e,0x3f4e3d49,0x3f183f80,0x3f713f5c,0xbeac3f04,0x3edb3f78,0xbf67be79,0x3dc93f62,0xbf7fbef1,0xbf7fbef1,0xbdc9bf62,
0xbf75bf46,0x3e95bf22,0x3e95bf22,0x3f753f46,0x3f22be95,0x3f463f75,0x3f463f75,0xbf223e95,0x3ef13f7f,0xbf62bdc9,0xbf62bdc9,0xbef1bf7f,
0xbd493f5c,0xbf80bf04,0xbf2cbf78,0x3f3ebe79,0xbf4ebf67,0x3f18bedb,0x3f7d3eac,0x3e163f71,0x3f713e16,0x3eac3f7d,0xbedb3f18,0xbf67bf4e,
0xbe793f3e,0xbf78bf2c,0xbf04bf80,0x3f5cbd49,0xbe483f55,0xbf7bbf0e,0x3e48bf55,0x3f7b3f0e,0xbf0ebf7b,0x3f55be48,0x3f0e3f7b,0xbf553e48,
0x3f7b3f0e,0xbe483f55,0xbf7bbf0e,0x3e48bf55,0xbf553e48,0xbf0ebf7b,0x3f55be48,0x3f0e3f7b,0xbeac3f4e,0xbf71bf18,0x3f67be16,0x3edb3f7d,
0xbe79bf80,0x3f783d49,0xbf043f2c,0xbf5cbf3e,0x3f3e3f5c,0xbf2c3f04,0xbd49bf78,0x3f803e79,0xbf7dbedb,0x3e16bf67,0x3f183f71,0xbf4e3eac,
0xbef13f46,0xbf62bf22,0x3f623f22,0xbef13f46,0x3dc9bf75,0x3f7f3e95,0xbf7fbe95,0x3dc9bf75,0x3e953f7f,0xbf753dc9,0x3f75bdc9,0x3e953f7f,
0xbf22bf62,0x3f46bef1,0xbf463ef1,0xbf22bf62,0xbf183f3e,0xbf4ebf2c,0x3e163f80,0xbf7d3d49,0x3edbbf5c,0x3f673f04,0xbeacbf78,0x3f71be79,
0xbe793f71,0xbf78beac,0x3f043f67,0xbf5c3edb,0x3d49bf7d,0x3f803e16,0xbf2cbf4e,0x3f3ebf18,0xbf353f35,0xbf35bf35,0xbf353f35,0xbf35bf35,
0x3f35bf35,0x3f353f35,0x3f35bf35,0x3f353f35,0xbf353f35,0xbf35bf35,0xbf353f35,0xbf35bf35,0x3f35bf35,0x3f353f35,0x3f35bf35,0x3f353f35,
0xbf4e3f2c,0xbf18bf3e,0xbf7dbd49,0x3e16bf80,0x3f67bf04,0x3edb3f5c,0x3f713e79,0xbeac3f78,0xbf783eac,0xbe79bf71,0xbf5cbedb,0x3f04bf67,
0x3f80be16,0x3d493f7d,0x3f3e3f18,0xbf2c3f4e,0xbf623f22,0xbef1bf46,0xbef1bf46,0x3f62bf22,0x3f7fbe95,0x3dc93f75,0x3dc93f75,0xbf7f3e95,
0xbf75bdc9,0x3e95bf7f,0x3e95bf7f,0x3f753dc9,0x3f463ef1,0xbf223f62,0xbf223f62,0xbf46bef1,0xbf713f18,0xbeacbf4e,0x3edbbf7d,0x3f673e16,
0x3f78bd49,0xbe793f80,0xbf5c3f3e,0xbf04bf2c,0xbf2cbf04,0x3f3ebf5c,0x3f80be79,0xbd493f78,0x3e163f67,0xbf7d3edb,0xbf4ebeac,0x3f18bf71,
0xbf7b3f0e,0xbe48bf55,0x3f7bbf0e,0x3e483f55,0x3f553e48,0xbf0e3f7b,0xbf55be48,0x3f0ebf7b,0xbe48bf55,0x3f7bbf0e,0x3e483f55,0xbf7b3f0e,
0xbf0e3f7b,0xbf55be48,0x3f0ebf7b,0x3f553e48,0xbf803f04,0xbd49bf5c,0x3f3e3e79,0xbf2c3f78,0x3f183edb,0xbf4e3f67,0x3e16bf71,0x3f7dbeac,
0x3eacbf7d,0x3f71be16,0xbf673f4e,0xbedbbf18,0xbf783f2c,0xbe79bf3e,0x3f5c3d49,0xbf043f80,0xbf7f3ef1,0x3dc9bf62,0xbdc93f62,0xbf7f3ef1,
0x3e953f22,0xbf753f46,0x3f75bf46,0x3e953f22,0x3f46bf75,0x3f223e95,0xbf22be95,0x3f46bf75,0xbf623dc9,0x3ef1bf7f,0xbef13f7f,0xbf623dc9,
0xbf783edb,0x3e79bf67,0xbf5c3f71,0xbf04beac,0xbd493f4e,0xbf803f18,0x3f2c3e16,0xbf3e3f7d,0x3f7dbf3e,0x3e163f2c,0x3f18bf80,0x3f4ebd49,
0xbeacbf04,0x3f71bf5c,0xbf673e79,0x3edbbf78,0xbf6d3ec4,0x3ec4bf6d,0xbf6d3ec4,0x3ec4bf6d,0xbec43f6d,0xbf6d3ec4,0xbec43f6d,0xbf6d3ec4,
0x3f6dbec4,0xbec43f6d,0x3f6dbec4,0xbec43f6d,0x3ec4bf6d,0x3f6dbec4,0x3ec4bf6d,0x3f6dbec4,0xbf5c3eac,0x3f04bf71,0xbe79bedb,0x3f78bf67,
0xbf2c3f7d,0xbf3e3e16,0xbf803f4e,0xbd49bf18,0x3f183d49,0xbf4e3f80,0xbe163f3e,0xbf7d3f2c,0x3f67bf78,0x3edb3e79,0x3f71bf04,0xbeac3f5c,
0xbf463e95,0x3f22bf75,0x3f22bf75,0x3f46be95,0xbf623f7f,0xbef1bdc9,0xbef1bdc9,0x3f62bf7f,0x3dc93ef1,0xbf7f3f62,0xbf7f3f62,0xbdc9bef1,
0x3f75bf22,0xbe953f46,0xbe953f46,0xbf753f22,0xbf2c3e79,0x3f3ebf78,0x3f80bf5c,0xbd493f04,0xbf7d3f71,0xbe16beac,0x3f18bf67,0x3f4ebedb,
0xbedb3f4e,0xbf673f18,0xbeacbe16,0x3f71bf7d,0x3f04bd49,0xbf5c3f80,0xbf783f3e,0x3e79bf2c,0xbf0e3e48,0x3f55bf7b,0x3f0ebe48,0xbf553f7b,
0xbf7b3f55,0x3e48bf0e,0x3f7bbf55,0xbe483f0e,0xbf553f7b,0xbf0e3e48,0x3f55bf7b,0x3f0ebe48,0xbe483f0e,0xbf7b3f55,0x3e48bf0e,0x3f7bbf55,
0xbedb3e16,0x3f67bf7d,0xbeac3f18,0xbf713f4e,0xbf5c3f2c,0x3f04bf3e,0x3e793d49,0xbf783f80,0xbf803f78,0xbd49be79,0x3f3ebf04,0xbf2c3f5c,
0xbf4e3f71,0xbf183eac,0x3f7dbf67,0xbe163edb,0xbe953dc9,0x3f75bf7f,0xbf753f7f,0xbe953dc9,0xbf223ef1,0x3f46bf62,0xbf463f62,0xbf223ef1,
0xbf623f46,0x3ef1bf22,0xbef13f22,0xbf623f46,0xbf7f3f75,0x3dc9be95,0xbdc93e95,0xbf7f3f75,0xbe163d49,0x3f7dbf80,0xbf4e3f3e,0x3f18bf2c,
0xbeac3e79,0x3f71bf78,0xbf673f5c,0x3edbbf04,0xbf043edb,0x3f5cbf67,0xbf783f71,0x3e79beac,0xbf2c3f18,0x3f3ebf4e,0xbf803f7d,0x3d49be16,
0x3f803f80,0xbf803f80,0x3f803f80,0xbf803f80,0x3f803f80,0xbf803f80,0x3f803f80,0xbf803f80,0x3f803f80,0xbf803f80,0x3f803f80,0xbf803f80,
0x3f803f80,0xbf803f80,0x3f803f80,0xbf803f80,0xbe16bd49,0xbf7dbf80,0xbf4ebf3e,0xbf18bf2c,0xbeacbe79,0xbf71bf78,0xbf67bf5c,0xbedbbf04,
0xbf04bedb,0xbf5cbf67,0xbf78bf71,0xbe79beac,0xbf2cbf18,0xbf3ebf4e,0xbf80bf7d,0xbd49be16,0xbf75bf7f,0x3e953dc9,0x3e953dc9,0x3f753f7f,
0xbf46bf62,0x3f223ef1,0x3f223ef1,0x3f463f62,0xbef1bf22,0x3f623f46,0x3f623f46,0x3ef13f22,0xbdc9be95,0x3f7f3f75,0x3f7f3f75,0x3dc93e95,
0x3edb3e16,0x3f673f7d,0x3eac3f18,0xbf71bf4e,0x3f5c3f2c,0x3f043f3e,0xbe793d49,0xbf78bf80,0x3f803f78,0xbd493e79,0xbf3ebf04,0xbf2cbf5c,
0x3f4e3f71,0xbf18beac,0xbf7dbf67,0xbe16bedb,0x3f553f7b,0xbf0ebe48,0xbf55bf7b,0x3f0e3e48,0x3e483f0e,0xbf7bbf55,0xbe48bf0e,0x3f7b3f55,
0xbf0ebe48,0xbf55bf7b,0x3f0e3e48,0x3f553f7b,0xbf7bbf55,0xbe48bf0e,0x3f7b3f55,0x3e483f0e,0xbf2cbe79,0xbf3ebf78,0x3f803f5c,0x3d493f04,
0xbf7dbf71,0x3e16beac,0x3f183f67,0xbf4ebedb,0xbedbbf4e,0x3f673f18,0xbeac3e16,0xbf71bf7d,0x3f043d49,0x3f5c3f80,0xbf78bf3e,0xbe79bf2c,
0xbf22bf75,0x3f463e95,0xbf46be95,0xbf22bf75,0x3ef1bdc9,0x3f623f7f,0xbf62bf7f,0x3ef1bdc9,0x3f7f3f62,0xbdc93ef1,0x3dc9bef1,0x3f7f3f62,
0x3e953f46,0xbf75bf22,0x3f753f22,0x3e953f46,0x3f5c3eac,0x3f043f71,0x3e79bedb,0x3f783f67,0x3f2c3f7d,0xbf3ebe16,0x3f803f4e,0xbd493f18,
0xbf183d49,0xbf4ebf80,0x3e163f3e,0xbf7dbf2c,0xbf67bf78,0x3edbbe79,0xbf71bf04,0xbeacbf5c,0x3ec43f6d,0xbf6dbec4,0x3ec43f6d,0xbf6dbec4,
0xbf6dbec4,0xbec4bf6d,0xbf6dbec4,0xbec4bf6d,0xbec4bf6d,0x3f6d3ec4,0xbec4bf6d,0x3f6d3ec4,0x3f6d3ec4,0x3ec43f6d,0x3f6d3ec4,0x3ec43f6d,
0xbf78bedb,0xbe79bf67,0xbf5cbf71,0x3f04beac,0xbd49bf4e,0x3f803f18,0x3f2cbe16,0x3f3e3f7d,0x3f7d3f3e,0xbe163f2c,0x3f183f80,0xbf4ebd49,
0xbeac3f04,0xbf71bf5c,0xbf67be79,0xbedbbf78,0xbdc9bf62,0x3f7f3ef1,0x3f7f3ef1,0x3dc93f62,0x3f753f46,0xbe953f22,0xbe953f22,0xbf75bf46,
0xbf223e95,0xbf46bf75,0xbf46bf75,0x3f22be95,0xbef1bf7f,0x3f623dc9,0x3f623dc9,0x3ef13f7f,0x3f803f04,0xbd493f5c,0xbf3e3e79,0xbf2cbf78,
0xbf183edb,0xbf4ebf67,0xbe16bf71,0x3f7d3eac,0xbeacbf7d,0x3f713e16,0x3f673f4e,0xbedb3f18,0x3f783f2c,0xbe793f3e,0xbf5c3d49,0xbf04bf80,
0xbe483f55,0xbf7bbf0e,0x3e48bf55,0x3f7b3f0e,0xbf0ebf7b,0x3f55be48,0x3f0e3f7b,0xbf553e48,0x3f7b3f0e,0xbe483f55,0xbf7bbf0e,0x3e48bf55,
0xbf553e48,0xbf0ebf7b,0x3f55be48,0x3f0e3f7b,0xbf71bf18,0x3eacbf4e,0x3edb3f7d,0xbf673e16,0x3f783d49,0x3e793f80,0xbf5cbf3e,0x3f04bf2c,
0xbf2c3f04,0xbf3ebf5c,0x3f803e79,0x3d493f78,0x3e16bf67,0x3f7d3edb,0xbf4e3eac,0xbf18bf71,0x3ef1bf46,0x3f623f22,0xbf62bf22,0x3ef1bf46,
0xbdc93f75,0xbf7fbe95,0x3f7f3e95,0xbdc93f75,0xbe95bf7f,0x3f75bdc9,0xbf753dc9,0xbe95bf7f,0x3f223f62,0xbf463ef1,0x3f46bef1,0x3f223f62,
0x3f4e3f2c,0xbf183f3e,0x3f7dbd49,0x3e163f80,0xbf67bf04,0x3edbbf5c,0xbf713e79,0xbeacbf78,0x3f783eac,0xbe793f71,0x3f5cbedb,0x3f043f67,
0xbf80be16,0x3d49bf7d,0xbf3e3f18,0xbf2cbf4e,0xbf353f35,0xbf35bf35,0xbf353f35,0xbf35bf35,0x3f35bf35,0x3f353f35,0x3f35bf35,0x3f353f35,
0xbf353f35,0xbf35bf35,0xbf353f35,0xbf35bf35,0x3f35bf35,0x3f353f35,0x3f35bf35,0x3f353f35,0xbf18bf3e,0x3f4ebf2c,0x3e16bf80,0x3f7d3d49,
0x3edb3f5c,0xbf673f04,0xbeac3f78,0xbf71be79,0xbe79bf71,0x3f78beac,0x3f04bf67,0x3f5c3edb,0x3d493f7d,0xbf803e16,0xbf2c3f4e,0xbf3ebf18,
0x3f62bf22,0x3ef13f46,0x3ef13f46,0xbf623f22,0xbf7f3e95,0xbdc9bf75,0xbdc9bf75,0x3f7fbe95,0x3f753dc9,0xbe953f7f,0xbe953f7f,0xbf75bdc9,
0xbf46bef1,0x3f22bf62,0x3f22bf62,0x3f463ef1,0x3eac3f4e,0xbf713f18,0xbf67be16,0x3edbbf7d,0x3e79bf80,0x3f78bd49,0x3f043f2c,0xbf5c3f3e,
0xbf3e3f5c,0xbf2cbf04,0x3d49bf78,0x3f80be79,0x3f7dbedb,0x3e163f67,0xbf183f71,0xbf4ebeac,0xbf7b3f0e,0xbe48bf55,0x3f7bbf0e,0x3e483f55,
0x3f553e48,0xbf0e3f7b,0xbf55be48,0x3f0ebf7b,0xbe48bf55,0x3f7bbf0e,0x3e483f55,0xbf7b3f0e,0xbf0e3f7b,0xbf55be48,0x3f0ebf7b,0x3f553e48,
0xbd49bf5c,0x3f80bf04,0xbf2c3f78,0xbf3ebe79,0xbf4e3f67,0xbf18bedb,0x3f7dbeac,0xbe163f71,0x3f71be16,0xbeac3f7d,0xbedbbf18,0x3f67bf4e,
0xbe79bf3e,0x3f78bf2c,0xbf043f80,0xbf5cbd49,0x3f7fbef1,0xbdc93f62,0x3dc9bf62,0x3f7fbef1,0xbe95bf22,0x3f75bf46,0xbf753f46,0xbe95bf22,
0xbf463f75,0xbf22be95,0x3f223e95,0xbf463f75,0x3f62bdc9,0xbef13f7f,0x3ef1bf7f,0x3f62bdc9,0xbe793f67,0xbf783edb,0x3f043eac,0xbf5c3f71,
0x3f80bf18,0xbd493f4e,0x3f3ebf7d,0x3f2c3e16,0xbe16bf2c,0x3f7dbf3e,0xbf4e3d49,0x3f18bf80,0xbf713f5c,0xbeacbf04,0xbedb3f78,0xbf673e79,
0xbf6d3ec4,0x3ec4bf6d,0xbf6d3ec4,0x3ec4bf6d,0xbec43f6d,0xbf6d3ec4,0xbec43f6d,0xbf6d3ec4,0x3f6dbec4,0xbec43f6d,0x3f6dbec4,0xbec43f6d,
0x3ec4bf6d,0x3f6dbec4,0x3ec4bf6d,0x3f6dbec4,0x3f04bf71,0x3f5cbeac,0x3f78bf67,0x3e793edb,0xbf3e3e16,0x3f2cbf7d,0xbd49bf18,0x3f80bf4e,
0xbf4e3f80,0xbf18bd49,0xbf7d3f2c,0x3e16bf3e,0x3edb3e79,0xbf673f78,0xbeac3f5c,0xbf713f04,0x3f46be95,0xbf223f75,0xbf223f75,0xbf463e95,
0x3f62bf7f,0x3ef13dc9,0x3ef13dc9,0xbf623f7f,0xbdc9bef1,0x3f7fbf62,0x3f7fbf62,0x3dc93ef1,0xbf753f22,0x3e95bf46,0x3e95bf46,0x3f75bf22,
0xbf3e3f78,0xbf2c3e79,0x3d49bf04,0x3f80bf5c,0x3e163eac,0xbf7d3f71,0xbf4e3edb,0x3f18bf67,0x3f67bf18,0xbedb3f4e,0xbf713f7d,0xbeacbe16,
0x3f5cbf80,0x3f04bd49,0xbe793f2c,0xbf783f3e,0xbf0e3e48,0x3f55bf7b,0x3f0ebe48,0xbf553f7b,0xbf7b3f55,0x3e48bf0e,0x3f7bbf55,0xbe483f0e,
0xbf553f7b,0xbf0e3e48,0x3f55bf7b,0x3f0ebe48,0xbe483f0e,0xbf7b3f55,0x3e48bf0e,0x3f7bbf55,0x3f67bf7d,0x3edbbe16,0xbf713f4e,0x3eacbf18,
0x3f04bf3e,0x3f5cbf2c,0xbf783f80,0xbe79bd49,0xbd49be79,0x3f80bf78,0xbf2c3f5c,0xbf3e3f04,0xbf183eac,0x3f4ebf71,0xbe163edb,0xbf7d3f67,
0x3e95bdc9,0xbf753f7f,0x3f75bf7f,0x3e95bdc9,0x3f22bef1,0xbf463f62,0x3f46bf62,0x3f22bef1,0x3f62bf46,0xbef13f22,0x3ef1bf22,0x3f62bf46,
0x3f7fbf75,0xbdc93e95,0x3dc9be95,0x3f7fbf75,0xbf7d3f80,0xbe163d49,0xbf183f2c,0xbf4e3f3e,0xbf713f78,0xbeac3e79,0xbedb3f04,0xbf673f5c,
0xbf5c3f67,0xbf043edb,0xbe793eac,0xbf783f71,0xbf3e3f4e,0xbf2c3f18,0xbd493e16,0xbf803f7d,0x3f803f80,0xbf803f80,0x3f803f80,0xbf803f80,
0x3f803f80,0xbf803f80,0x3f803f80,0xbf803f80,0x3f803f80,0xbf803f80,0x3f803f80,0xbf803f80,0x3f803f80,0xbf803f80,0x3f803f80,0xbf803f80,
0xbf7dbf80,0x3e163d49,0xbf18bf2c,0x3f4e3f3e,0xbf71bf78,0x3eac3e79,0xbedbbf04,0x3f673f5c,0xbf5cbf67,0x3f043edb,0xbe79beac,0x3f783f71,
0xbf3ebf4e,0x3f2c3f18,0xbd49be16,0x3f803f7d,0x3f753f7f,0xbe95bdc9,0xbe95bdc9,0xbf75bf7f,0x3f463f62,0xbf22bef1,0xbf22bef1,0xbf46bf62,
0x3ef13f22,0xbf62bf46,0xbf62bf46,0xbef1bf22,0x3dc93e95,0xbf7fbf75,0xbf7fbf75,0xbdc9be95,0xbf67bf7d,0x3edb3e16,0x3f713f4e,0x3eac3f18,
0xbf04bf3e,0x3f5c3f2c,0x3f783f80,0xbe793d49,0x3d49be79,0x3f803f78,0x3f2c3f5c,0xbf3ebf04,0x3f183eac,0x3f4e3f71,0x3e163edb,0xbf7dbf67,
0x3f553f7b,0xbf0ebe48,0xbf55bf7b,0x3f0e3e48,0x3e483f0e,0xbf7bbf55,0xbe48bf0e,0x3f7b3f55,0xbf0ebe48,0xbf55bf7b,0x3f0e3e48,0x3f553f7b,
0xbf7bbf55,0xbe48bf0e,0x3f7b3f55,0x3e483f0e,0xbf3ebf78,0x3f2c3e79,0x3d493f04,0xbf80bf5c,0x3e16beac,0x3f7d3f71,0xbf4ebedb,0xbf18bf67,
0x3f673f18,0x3edb3f4e,0xbf71bf7d,0x3eacbe16,0x3f5c3f80,0xbf04bd49,0xbe79bf2c,0x3f783f3e,0x3f223f75,0xbf46be95,0x3f463e95,0x3f223f75,
0xbef13dc9,0xbf62bf7f,0x3f623f7f,0xbef13dc9,0xbf7fbf62,0x3dc9bef1,0xbdc93ef1,0xbf7fbf62,0xbe95bf46,0x3f753f22,0xbf75bf22,0xbe95bf46,
0xbf04bf71,0x3f5c3eac,0xbf78bf67,0x3e79bedb,0x3f3e3e16,0x3f2c3f7d,0x3d49bf18,0x3f803f4e,0x3f4e3f80,0xbf183d49,0x3f7d3f2c,0x3e163f3e,
0xbedb3e79,0xbf67bf78,0x3eac3f5c,0xbf71bf04,0x3ec43f6d,0xbf6dbec4,0x3ec43f6d,0xbf6dbec4,0xbf6dbec4,0xbec4bf6d,0xbf6dbec4,0xbec4bf6d,
0xbec4bf6d,0x3f6d3ec4,0xbec4bf6d,0x3f6d3ec4,0x3f6d3ec4,0x3ec43f6d,0x3f6d3ec4,0x3ec43f6d,0xbe79bf67,0x3f783edb,0x3f04beac,0x3f5c3f71,
0x3f803f18,0x3d493f4e,0x3f3e3f7d,0xbf2c3e16,0xbe163f2c,0xbf7dbf3e,0xbf4ebd49,0xbf18bf80,0xbf71bf5c,0x3eacbf04,0xbedbbf78,0x3f673e79,
0x3dc93f62,0xbf7fbef1,0xbf7fbef1,0xbdc9bf62,0xbf75bf46,0x3e95bf22,0x3e95bf22,0x3f753f46,0x3f22be95,0x3f463f75,0x3f463f75,0xbf223e95,
0x3ef13f7f,0xbf62bdc9,0xbf62bdc9,0xbef1bf7f,0x3d49bf5c,0x3f803f04,0x3f2c3f78,0xbf3e3e79,0x3f4e3f67,0xbf183edb,0xbf7dbeac,0xbe16bf71,
0xbf71be16,0xbeacbf7d,0x3edbbf18,0x3f673f4e,0x3e79bf3e,0x3f783f2c,0x3f043f80,0xbf5c3d49,0xbe483f55,0xbf7bbf0e,0x3e48bf55,0x3f7b3f0e,
0xbf0ebf7b,0x3f55be48,0x3f0e3f7b,0xbf553e48,0x3f7b3f0e,0xbe483f55,0xbf7bbf0e,0x3e48bf55,0xbf553e48,0xbf0ebf7b,0x3f55be48,0x3f0e3f7b,
0x3eacbf4e,0x3f713f18,0xbf673e16,0xbedbbf7d,0x3e793f80,0xbf78bd49,0x3f04bf2c,0x3f5c3f3e,0xbf3ebf5c,0x3f2cbf04,0x3d493f78,0xbf80be79,
0x3f7d3edb,0xbe163f67,0xbf18bf71,0x3f4ebeac,0xbef13f46,0xbf62bf22,0x3f623f22,0xbef13f46,0x3dc9bf75,0x3f7f3e95,0xbf7fbe95,0x3dc9bf75,
0x3e953f7f,0xbf753dc9,0x3f75bdc9,0x3e953f7f,0xbf22bf62,0x3f46bef1,0xbf463ef1,0xbf22bf62,0x3f18bf3e,0x3f4e3f2c,0xbe16bf80,0x3f7dbd49,
0xbedb3f5c,0xbf67bf04,0x3eac3f78,0xbf713e79,0x3e79bf71,0x3f783eac,0xbf04bf67,0x3f5cbedb,0xbd493f7d,0xbf80be16,0x3f2c3f4e,0xbf3e3f18,
0xbf353f35,0xbf35bf35,0xbf353f35,0xbf35bf35,0x3f35bf35,0x3f353f35,0x3f35bf35,0x3f353f35,0xbf353f35,0xbf35bf35,0xbf353f35,0xbf35bf35,
0x3f35bf35,0x3f353f35,0x3f35bf35,0x3f353f35,0x3f4ebf2c,0x3f183f3e,0x3f7d3d49,0xbe163f80,0xbf673f04,0xbedbbf5c,0xbf71be79,0x3eacbf78,
0x3f78beac,0x3e793f71,0x3f5c3edb,0xbf043f67,0xbf803e16,0xbd49bf7d,0xbf3ebf18,0x3f2cbf4e,0xbf623f22,0xbef1bf46,0xbef1bf46,0x3f62bf22,
0x3f7fbe95,0x3dc93f75,0x3dc93f75,0xbf7f3e95,0xbf75bdc9,0x3e95bf7f,0x3e95bf7f,0x3f753dc9,0x3f463ef1,0xbf223f62,0xbf223f62,0xbf46bef1,
0x3f71bf18,0x3eac3f4e,0xbedb3f7d,0xbf67be16,0xbf783d49,0x3e79bf80,0x3f5cbf3e,0x3f043f2c,0x3f2c3f04,0xbf3e3f5c,0xbf803e79,0x3d49bf78,
0xbe16bf67,0x3f7dbedb,0x3f4e3eac,0xbf183f71,0xbf7b3f0e,0xbe48bf55,0x3f7bbf0e,0x3e483f55,0x3f553e48,0xbf0e3f7b,0xbf55be48,0x3f0ebf7b,
0xbe48bf55,0x3f7bbf0e,0x3e483f55,0xbf7b3f0e,0xbf0e3f7b,0xbf55be48,0x3f0ebf7b,0x3f553e48,0x3f80bf04,0x3d493f5c,0xbf3ebe79,0x3f2cbf78,
0xbf18bedb,0x3f4ebf67,0xbe163f71,0xbf7d3eac,0xbeac3f7d,0xbf713e16,0x3f67bf4e,0x3edb3f18,0x3f78bf2c,0x3e793f3e,0xbf5cbd49,0x3f04bf80,
0xbf7f3ef1,0x3dc9bf62,0xbdc93f62,0xbf7f3ef1,0x3e953f22,0xbf753f46,0x3f75bf46,0x3e953f22,0x3f46bf75,0x3f223e95,0xbf22be95,0x3f46bf75,
0xbf623dc9,0x3ef1bf7f,0xbef13f7f,0xbf623dc9,0x3f78bedb,0xbe793f67,0x3f5cbf71,0x3f043eac,0x3d49bf4e,0x3f80bf18,0xbf2cbe16,0x3f3ebf7d,
0xbf7d3f3e,0xbe16bf2c,0xbf183f80,0xbf4e3d49,0x3eac3f04,0xbf713f5c,0x3f67be79,0xbedb3f78,0xbf6d3ec4,0x3ec4bf6d,0xbf6d3ec4,0x3ec4bf6d,
0xbec43f6d,0xbf6d3ec4,0xbec43f6d,0xbf6d3ec4,0x3f6dbec4,0xbec43f6d,0x3f6dbec4,0xbec43f6d,0x3ec4bf6d,0x3f6dbec4,0x3ec4bf6d,0x3f6dbec4,
0x3f5cbeac,0xbf043f71,0x3e793edb,0xbf783f67,0x3f2cbf7d,0x3f3ebe16,0x3f80bf4e,0x3d493f18,0xbf18bd49,0x3f4ebf80,0x3e16bf3e,0x3f7dbf2c,
0xbf673f78,0xbedbbe79,0xbf713f04,0x3eacbf5c,0xbf463e95,0x3f22bf75,0x3f22bf75,0x3f46be95,0xbf623f7f,0xbef1bdc9,0xbef1bdc9,0x3f62bf7f,
0x3dc93ef1,0xbf7f3f62,0xbf7f3f62,0xbdc9bef1,0x3f75bf22,0xbe953f46,0xbe953f46,0xbf753f22,0x3f2cbe79,0xbf3e3f78,0xbf803f5c,0x3d49bf04,
0x3f7dbf71,0x3e163eac,0xbf183f67,0xbf4e3edb,0x3edbbf4e,0x3f67bf18,0x3eac3e16,0xbf713f7d,0xbf043d49,0x3f5cbf80,0x3f78bf3e,0xbe793f2c,
0xbf0e3e48,0x3f55bf7b,0x3f0ebe48,0xbf553f7b,0xbf7b3f55,0x3e48bf0e,0x3f7bbf55,0xbe483f0e,0xbf553f7b,0xbf0e3e48,0x3f55bf7b,0x3f0ebe48,
0xbe483f0e,0xbf7b3f55,0x3e48bf0e,0x3f7bbf55,0x3edbbe16,0xbf673f7d,0x3eacbf18,0x3f71bf4e,0x3f5cbf2c,0xbf043f3e,0xbe79bd49,0x3f78bf80,
0x3f80bf78,0x3d493e79,0xbf3e3f04,0x3f2cbf5c,0x3f4ebf71,0x3f18beac,0xbf7d3f67,0x3e16bedb,0xbe953dc9,0x3f75bf7f,0xbf753f7f,0xbe953dc9,
0xbf223ef1,0x3f46bf62,0xbf463f62,0xbf223ef1,0xbf623f46,0x3ef1bf22,0xbef13f22,0xbf623f46,0xbf7f3f75,0x3dc9be95,0xbdc93e95,0xbf7f3f75,
0x3e16bd49,0xbf7d3f80,0x3f4ebf3e,0xbf183f2c,0x3eacbe79,0xbf713f78,0x3f67bf5c,0xbedb3f04,0x3f04bedb,0xbf5c3f67,0x3f78bf71,0xbe793eac,
0x3f2cbf18,0xbf3e3f4e,0x3f80bf7d,0xbd493e16,0x3f803f80,0xbf803f80,0x3f803f80,0xbf803f80,0x3f803f80,0xbf803f80,0x3f803f80,0xbf803f80,
0x3f803f80,0xbf803f80,0x3f803f80,0xbf803f80,0x3f803f80,0xbf803f80,0x3f803f80,0xbf803f80,0x3e163d49,0x3f7d3f80,0x3f4e3f3e,0x3f183f2c,
0x3eac3e79,0x3f713f78,0x3f673f5c,0x3edb3f04,0x3f043edb,0x3f5c3f67,0x3f783f71,0x3e793eac,0x3f2c3f18,0x3f3e3f4e,0x3f803f7d,0x3d493e16,
0xbf75bf7f,0x3e953dc9,0x3e953dc9,0x3f753f7f,0xbf46bf62,0x3f223ef1,0x3f223ef1,0x3f463f62,0xbef1bf22,0x3f623f46,0x3f623f46,0x3ef13f22,
0xbdc9be95,0x3f7f3f75,0x3f7f3f75,0x3dc93e95,0xbedbbe16,0xbf67bf7d,0xbeacbf18,0x3f713f4e,0xbf5cbf2c,0xbf04bf3e,0x3e79bd49,0x3f783f80,
0xbf80bf78,0x3d49be79,0x3f3e3f04,0x3f2c3f5c,0xbf4ebf71,0x3f183eac,0x3f7d3f67,0x3e163edb,0x3f553f7b,0xbf0ebe48,0xbf55bf7b,0x3f0e3e48,
0x3e483f0e,0xbf7bbf55,0xbe48bf0e,0x3f7b3f55,0xbf0ebe48,0xbf55bf7b,0x3f0e3e48,0x3f553f7b,0xbf7bbf55,0xbe48bf0e,0x3f7b3f55,0x3e483f0e,
0x3f2c3e79,0x3f3e3f78,0xbf80bf5c,0xbd49bf04,0x3f7d3f71,0xbe163eac,0xbf18bf67,0x3f4e3edb,0x3edb3f4e,0xbf67bf18,0x3eacbe16,0x3f713f7d,
0xbf04bd49,0xbf5cbf80,0x3f783f3e,0x3e793f2c,0xbf22bf75,0x3f463e95,0xbf46be95,0xbf22bf75,0x3ef1bdc9,0x3f623f7f,0xbf62bf7f,0x3ef1bdc9,
0x3f7f3f62,0xbdc93ef1,0x3dc9bef1,0x3f7f3f62,0x3e953f46,0xbf75bf22,0x3f753f22,0x3e953f46,0xbf5cbeac,0xbf04bf71,0xbe793edb,0xbf78bf67,
0xbf2cbf7d,0x3f3e3e16,0xbf80bf4e,0x3d49bf18,0x3f18bd49,0x3f4e3f80,0xbe16bf3e,0x3f7d3f2c,0x3f673f78,0xbedb3e79,0x3f713f04,0x3eac3f5c,
0x3ec43f6d,0xbf6dbec4,0x3ec43f6d,0xbf6dbec4,0xbf6dbec4,0xbec4bf6d,0xbf6dbec4,0xbec4bf6d,0xbec4bf6d,0x3f6d3ec4,0xbec4bf6d,0x3f6d3ec4,
0x3f6d3ec4,0x3ec43f6d,0x3f6d3ec4,0x3ec43f6d,0x3f783edb,0x3e793f67,0x3f5c3f71,0xbf043eac,0x3d493f4e,0xbf80bf18,0xbf2c3e16,0xbf3ebf7d,
0xbf7dbf3e,0x3e16bf2c,0xbf18bf80,0x3f4e3d49,0x3eacbf04,0x3f713f5c,0x3f673e79,0x3edb3f78,0xbdc9bf62,0x3f7f3ef1,0x3f7f3ef1,0x3dc93f62,
0x3f753f46,0xbe953f22,0xbe953f22,0xbf75bf46,0xbf223e95,0xbf46bf75,0xbf46bf75,0x3f22be95,0xbef1bf7f,0x3f623dc9,0x3f623dc9,0x3ef13f7f,
0xbf80bf04,0x3d49bf5c,0x3f3ebe79,0x3f2c3f78,0x3f18bedb,0x3f4e3f67,0x3e163f71,0xbf7dbeac,0x3eac3f7d,0xbf71be16,0xbf67bf4e,0x3edbbf18,
0xbf78bf2c,0x3e79bf3e,0x3f5cbd49,0x3f043f80,0xbe483f55,0xbf7bbf0e,0x3e48bf55,0x3f7b3f0e,0xbf0ebf7b,0x3f55be48,0x3f0e3f7b,0xbf553e48,
0x3f7b3f0e,0xbe483f55,0xbf7bbf0e,0x3e48bf55,0xbf553e48,0xbf0ebf7b,0x3f55be48,0x3f0e3f7b,0x3f713f18,0xbeac3f4e,0xbedbbf7d,0x3f67be16,
0xbf78bd49,0xbe79bf80,0x3f5c3f3e,0xbf043f2c,0x3f2cbf04,0x3f3e3f5c,0xbf80be79,0xbd49bf78,0xbe163f67,0xbf7dbedb,0x3f4ebeac,0x3f183f71,
0x3ef1bf46,0x3f623f22,0xbf62bf22,0x3ef1bf46,0xbdc93f75,0xbf7fbe95,0x3f7f3e95,0xbdc93f75,0xbe95bf7f,0x3f75bdc9,0xbf753dc9,0xbe95bf7f,
0x3f223f62,0xbf463ef1,0x3f46bef1,0x3f223f62,0xbf4ebf2c,0x3f18bf3e,0xbf7d3d49,0xbe16bf80,0x3f673f04,0xbedb3f5c,0x3f71be79,0x3eac3f78,
0xbf78beac,0x3e79bf71,0xbf5c3edb,0xbf04bf67,0x3f803e16,0xbd493f7d,0x3f3ebf18,0x3f2c3f4e,0xbf353f35,0xbf35bf35,0xbf353f35,0xbf35bf35,
0x3f35bf35,0x3f353f35,0x3f35bf35,0x3f353f35,0xbf353f35,0xbf35bf35,0xbf353f35,0xbf35bf35,0x3f35bf35,0x3f353f35,0x3f35bf35,0x3f353f35,
0x3f183f3e,0xbf4e3f2c,0xbe163f80,0xbf7dbd49,0xbedbbf5c,0x3f67bf04,0x3eacbf78,0x3f713e79,0x3e793f71,0xbf783eac,0xbf043f67,0xbf5cbedb,
0xbd49bf7d,0x3f80be16,0x3f2cbf4e,0x3f3e3f18,0x3f62bf22,0x3ef13f46,0x3ef13f46,0xbf623f22,0xbf7f3e95,0xbdc9bf75,0xbdc9bf75,0x3f7fbe95,
0x3f753dc9,0xbe953f7f,0xbe953f7f,0xbf75bdc9,0xbf46bef1,0x3f22bf62,0x3f22bf62,0x3f463ef1,0xbeacbf4e,0x3f71bf18,0x3f673e16,0xbedb3f7d,
0xbe793f80,0xbf783d49,0xbf04bf2c,0x3f5cbf3e,0x3f3ebf5c,0x3f2c3f04,0xbd493f78,0xbf803e79,0xbf7d3edb,0xbe16bf67,0x3f18bf71,0x3f4e3eac,
0xbf7b3f0e,0xbe48bf55,0x3f7bbf0e,0x3e483f55,0x3f553e48,0xbf0e3f7b,0xbf55be48,0x3f0ebf7b,0xbe48bf55,0x3f7bbf0e,0x3e483f55,0xbf7b3f0e,
0xbf0e3f7b,0xbf55be48,0x3f0ebf7b,0x3f553e48,0x3d493f5c,0xbf803f04,0x3f2cbf78,0x3f3e3e79,0x3f4ebf67,0x3f183edb,0xbf7d3eac,0x3e16bf71,
0xbf713e16,0x3eacbf7d,0x3edb3f18,0xbf673f4e,0x3e793f3e,0xbf783f2c,0x3f04bf80,0x3f5c3d49,0x3f7fbef1,0xbdc93f62,0x3dc9bf62,0x3f7fbef1,
0xbe95bf22,0x3f75bf46,0xbf753f46,0xbe95bf22,0xbf463f75,0xbf22be95,0x3f223e95,0xbf463f75,0x3f62bdc9,0xbef13f7f,0x3ef1bf7f,0x3f62bdc9,
0x3e79bf67,0x3f78bedb,0xbf04beac,0x3f5cbf71,0xbf803f18,0x3d49bf4e,0xbf3e3f7d,0xbf2cbe16,0x3e163f2c,0xbf7d3f3e,0x3f4ebd49,0xbf183f80,
0x3f71bf5c,0x3eac3f04,0x3edbbf78,0x3f67be79,0xbf6d3ec4,0x3ec4bf6d,0xbf6d3ec4,0x3ec4bf6d,0xbec43f6d,0xbf6d3ec4,0xbec43f6d,0xbf6d3ec4,
0x3f6dbec4,0xbec43f6d,0x3f6dbec4,0xbec43f6d,0x3ec4bf6d,0x3f6dbec4,0x3ec4bf6d,0x3f6dbec4,0xbf043f71,0xbf5c3eac,0xbf783f67,0xbe79bedb,
0x3f3ebe16,0xbf2c3f7d,0x3d493f18,0xbf803f4e,0x3f4ebf80,0x3f183d49,0x3f7dbf2c,0xbe163f3e,0xbedbbe79,0x3f67bf78,0x3eacbf5c,0x3f71bf04,
0x3f46be95,0xbf223f75,0xbf223f75,0xbf463e95,0x3f62bf7f,0x3ef13dc9,0x3ef13dc9,0xbf623f7f,0xbdc9bef1,0x3f7fbf62,0x3f7fbf62,0x3dc93ef1,
0xbf753f22,0x3e95bf46,0x3e95bf46,0x3f75bf22,0x3f3ebf78,0x3f2cbe79,0xbd493f04,0xbf803f5c,0xbe16beac,0x3f7dbf71,0x3f4ebedb,0xbf183f67,
0xbf673f18,0x3edbbf4e,0x3f71bf7d,0x3eac3e16,0xbf5c3f80,0xbf043d49,0x3e79bf2c,0x3f78bf3e,0xbf0e3e48,0x3f55bf7b,0x3f0ebe48,0xbf553f7b,
0xbf7b3f55,0x3e48bf0e,0x3f7bbf55,0xbe483f0e,0xbf553f7b,0xbf0e3e48,0x3f55bf7b,0x3f0ebe48,0xbe483f0e,0xbf7b3f55,0x3e48bf0e,0x3f7bbf55,
0xbf673f7d,0xbedb3e16,0x3f71bf4e,0xbeac3f18,0xbf043f3e,0xbf5c3f2c,0x3f78bf80,0x3e793d49,0x3d493e79,0xbf803f78,0x3f2cbf5c,0x3f3ebf04,
0x3f18beac,0xbf4e3f71,0x3e16bedb,0x3f7dbf67,0x3e95bdc9,0xbf753f7f,0x3f75bf7f,0x3e95bdc9,0x3f22bef1,0xbf463f62,0x3f46bf62,0x3f22bef1,
0x3f62bf46,0xbef13f22,0x3ef1bf22,0x3f62bf46,0x3f7fbf75,0xbdc93e95,0x3dc9be95,0x3f7fbf75,0x3f7dbf80,0x3e16bd49,0x3f18bf2c,0x3f4ebf3e,
0x3f71bf78,0x3eacbe79,0x3edbbf04,0x3f67bf5c,0x3f5cbf67,0x3f04bedb,0x3e79beac,0x3f78bf71,0x3f3ebf4e,0x3f2cbf18,0x3d49be16,0x3f80bf7d,
0x3f803f80,0xbf353f35,0x3f803f80,0xbf353f35,0x3f803f80,0xbf353f35,0x3f803f80,0xbf353f35,0x3f803f80,0xbf353f35,0x3f803f80,0xbf353f35,
0x3f803f80,0xbf353f35,0x3f803f80,0xbf353f35,0x3f7c3f7f,0xbe2fbd97,0x3f133f27,0xbf51bf42,0x3f6f3f77,0xbeb8be89,0x3ecf3efc,0xbf6abf5f,
0x3f583f65,0xbf09bee6,0x3e603ea1,0xbf7abf73,0x3f393f4a,0xbf31bf1d,0x3cc93dfb,0xbf80bf7e,0x3f713f7d,0xbeacbe16,0xbeacbe16,0xbf71bf7d,
0x3f3e3f5c,0xbf2cbf04,0xbf2cbf04,0xbf3ebf5c,0x3edb3f18,0xbf67bf4e,0xbf67bf4e,0xbedbbf18,0x3d493e79,0xbf80bf78,0xbf80bf78,0xbd49be79,
0x3f5f3f7a,0xbefcbe60,0xbf77bf58,0xbe89bf09,0x3ee63f31,0xbf65bf39,0xbf73bf80,0x3ea13cc9,0xbdfb3e2f,0xbf7ebf7c,0xbf1dbf51,0x3f4a3f13,
0xbf27becf,0xbf42bf6a,0xbd97beb8,0x3f7f3f6f,0x3f463f75,0xbf22be95,0xbf46bf75,0x3f223e95,0x3dc93ef1,0xbf7fbf62,0xbdc9bef1,0x3f7f3f62,
0xbf22be95,0xbf46bf75,0x3f223e95,0x3f463f75,0xbf7fbf62,0xbdc9bef1,0x3f7f3f62,0x3dc93ef1,0x3f273f6f,0xbf42beb8,0x3d97becf,0x3f7f3f6a,
0xbe893e60,0xbf77bf7a,0x3f5f3f09,0x3efc3f58,0xbf73bf31,0xbea1bf39,0x3f653f80,0xbee63cc9,0xbf4abf7c,0x3f1d3e2f,0x3dfb3f13,0xbf7ebf51,
0x3f043f67,0xbf5cbedb,0x3f5c3edb,0x3f043f67,0xbf18bd49,0xbf4ebf80,0x3f4e3f80,0xbf18bd49,0xbf78bf71,0x3e79beac,0xbe793eac,0xbf78bf71,
0xbe16bf2c,0x3f7d3f3e,0xbf7dbf3e,0xbe16bf2c,0x3eb83f5f,0xbf6fbefc,0x3f6a3f77,0xbecf3e89,0xbf58bea1,0xbf09bf73,0xbe603ee6,0xbf7abf65,
0xbf31bf7e,0x3f393dfb,0xbf80bf4a,0x3cc9bf1d,0x3f13bd97,0x3f513f7f,0xbe2fbf42,0x3f7c3f27,0x3e483f55,0xbf7bbf0e,0x3e483f55,0xbf7bbf0e,
0xbf7bbf0e,0xbe48bf55,0xbf7bbf0e,0xbe48bf55,0xbe48bf55,0x3f7b3f0e,0xbe48bf55,0x3f7b3f0e,0x3f7b3f0e,0x3e483f55,0x3f7b3f0e,0x3e483f55,
0x3cc93f4a,0xbf80bf1d,0xbf313dfb,0xbf39bf7e,0xbf7cbf42,0x3e2fbf27,0xbf13bf7f,0x3f513d97,0x3eb8befc,0x3f6f3f5f,0x3f6a3e89,0x3ecf3f77,
0x3f583f73,0xbf093ea1,0x3e603f65,0xbf7abee6,0xbe163f3e,0xbf7dbf2c,0xbf7dbf2c,0x3e16bf3e,0xbf5cbf67,0x3f04bedb,0x3f04bedb,0x3f5c3f67,
0x3f4ebd49,0x3f183f80,0x3f183f80,0xbf4e3d49,0x3e793f71,0xbf78beac,0xbf78beac,0xbe79bf71,0xbea13f31,0xbf73bf39,0xbee6bf80,0x3f653cc9,
0xbf1dbf7c,0x3f4abe2f,0x3f7e3f13,0xbdfb3f51,0x3f7f3ecf,0x3d973f6a,0xbf273eb8,0xbf42bf6f,0xbefc3f09,0xbf5fbf58,0xbe89bf7a,0x3f773e60,
0xbef13f22,0xbf62bf46,0x3ef1bf22,0x3f623f46,0xbe95bf7f,0x3f753dc9,0x3e953f7f,0xbf75bdc9,0x3f623f46,0xbef13f22,0xbf62bf46,0x3ef1bf22,
0xbf75bdc9,0xbe95bf7f,0x3f753dc9,0x3e953f7f,0xbf1d3f13,0xbf4abf51,0x3f7e3e2f,0x3dfb3f7c,0x3d97bf6f,0x3f7f3eb8,0xbf423ecf,0xbf27bf6a,
0x3efc3f7a,0xbf5f3e60,0x3e89bf58,0x3f773f09,0xbf65bf31,0x3ee6bf39,0x3ea13f80,0xbf733cc9,0xbf3e3f04,0xbf2cbf5c,0x3f2c3f5c,0xbf3e3f04,
0x3edbbf4e,0x3f673f18,0xbf67bf18,0x3edbbf4e,0xbd493f78,0xbf80be79,0x3f803e79,0xbd493f78,0xbeacbf7d,0x3f71be16,0xbf713e16,0xbeacbf7d,
0xbf583ee6,0xbf09bf65,0xbe603f73,0xbf7abea1,0x3f39bf1d,0x3f313f4a,0x3cc9bf7e,0x3f803dfb,0xbf133f42,0xbf51bf27,0x3e2f3f7f,0xbf7c3d97,
0x3ecfbf5f,0x3f6a3efc,0xbeb8bf77,0x3f6fbe89,0xbf6d3ec4,0xbec4bf6d,0xbf6d3ec4,0xbec4bf6d,0x3f6dbec4,0x3ec43f6d,0x3f6dbec4,0x3ec43f6d,
0xbf6d3ec4,0xbec4bf6d,0xbf6d3ec4,0xbec4bf6d,0x3f6dbec4,0x3ec43f6d,0x3f6dbec4,0x3ec43f6d,0xbf7a3ea1,0xbe60bf73,0xbf58bee6,0x3f09bf65,
0x3f80bdfb,0x3cc93f7e,0x3f393f1d,0xbf313f4a,0xbf7cbd97,0x3e2fbf7f,0xbf13bf42,0x3f51bf27,0x3f6f3e89,0xbeb83f77,0x3ecf3f5f,0xbf6a3efc,
0xbf803e79,0xbd49bf78,0xbd49bf78,0x3f80be79,0x3f713e16,0xbeac3f7d,0xbeac3f7d,0xbf71be16,0xbf3ebf04,0x3f2cbf5c,0x3f2cbf5c,0x3f3e3f04,
0x3edb3f4e,0xbf673f18,0xbf673f18,0xbedbbf4e,0xbf7e3e2f,0x3dfbbf7c,0x3f4abf51,0x3f1d3f13,0x3f423ecf,0xbf273f6a,0xbf7f3eb8,0xbd97bf6f,
0xbe89bf58,0x3f77bf09,0x3f5f3e60,0xbefc3f7a,0xbea13f80,0xbf73bcc9,0xbee6bf39,0x3f65bf31,0xbf753dc9,0x3e95bf7f,0x3f75bdc9,0xbe953f7f,
0x3ef13f22,0xbf623f46,0xbef1bf22,0x3f62bf46,0x3e95bf7f,0x3f75bdc9,0xbe953f7f,0xbf753dc9,0xbf623f46,0xbef1bf22,0x3f62bf46,0x3ef13f22,
0xbf653cc9,0x3ee6bf80,0x3ea13f31,0xbf733f39,0x3dfb3f51,0xbf7e3f13,0x3f1dbf7c,0x3f4a3e2f,0x3f42bf6f,0x3f273eb8,0xbf7f3ecf,0x3d97bf6a,
0xbf773e60,0x3e89bf7a,0x3efc3f09,0xbf5f3f58,0xbf4ebd49,0x3f18bf80,0xbf183f80,0xbf4ebd49,0xbe793f71,0xbf783eac,0x3f78beac,0xbe793f71,
0x3f7dbf2c,0x3e163f3e,0xbe16bf3e,0x3f7dbf2c,0xbf04bedb,0x3f5cbf67,0xbf5c3f67,0xbf04bedb,0xbf31bdfb,0x3f39bf7e,0xbf803f1d,0x3cc9bf4a,
0xbf133f7f,0xbf513d97,0x3e2f3f27,0xbf7c3f42,0x3f6abe89,0xbecf3f77,0x3f6fbf5f,0x3eb83efc,0x3e60bf65,0x3f7abee6,0xbf09bea1,0x3f58bf73,
0xbf0ebe48,0x3f55bf7b,0xbf0ebe48,0x3f55bf7b,0xbf553f7b,0xbf0ebe48,0xbf553f7b,0xbf0ebe48,0x3f0e3e48,0xbf553f7b,0x3f0e3e48,0xbf553f7b,
0x3f55bf7b,0x3f0e3e48,0x3f55bf7b,0x3f0e3e48,0xbecfbe89,0x3f6abf77,0x3eb8bf5f,0x3f6fbefc,0xbf7a3f65,0xbe60bee6,0xbf583ea1,0x3f09bf73,
0x3cc93f1d,0xbf803f4a,0xbf313f7e,0xbf393dfb,0x3f7cbf27,0xbe2f3f42,0x3f133d97,0xbf513f7f,0xbe79beac,0x3f78bf71,0x3f78bf71,0x3e793eac,
0xbf7d3f3e,0x3e16bf2c,0x3e16bf2c,0x3f7dbf3e,0xbf043f67,0xbf5c3edb,0xbf5c3edb,0x3f04bf67,0x3f18bd49,0xbf4e3f80,0xbf4e3f80,0xbf183d49,
0xbd97becf,0x3f7fbf6a,0x3f42beb8,0xbf273f6f,0xbf5f3f09,0x3efcbf58,0x3f77bf7a,0x3e893e60,0xbf653f80,0xbee6bcc9,0x3ea1bf39,0x3f73bf31,
0xbdfb3f13,0xbf7e3f51,0xbf1d3e2f,0x3f4abf7c,0x3dc9bef1,0x3f7fbf62,0xbdc93ef1,0xbf7f3f62,0xbf223e95,0x3f46bf75,0x3f22be95,0xbf463f75,
0xbf7f3f62,0x3dc9bef1,0x3f7fbf62,0xbdc93ef1,0xbf463f75,0xbf223e95,0x3f46bf75,0x3f22be95,0x3e89bf09,0x3f77bf58,0xbf5f3f7a,0xbefc3e60,
0xbea13cc9,0x3f73bf80,0xbee63f31,0xbf653f39,0xbf4a3f13,0x3f1dbf51,0x3dfb3e2f,0xbf7e3f7c,0xbf7f3f6f,0x3d97beb8,0x3f27becf,0xbf423f6a,
0x3edbbf18,0x3f67bf4e,0xbf673f4e,0x3edbbf18,0x3d49be79,0x3f80bf78,0xbf803f78,0x3d49be79,0xbeac3e16,0x3f71bf7d,0xbf713f7d,0xbeac3e16,
0xbf2c3f04,0x3f3ebf5c,0xbf3e3f5c,0xbf2c3f04,0x3f13bf27,0x3f51bf42,0xbe2f3d97,0x3f7cbf7f,0x3ecfbefc,0x3f6abf5f,0xbeb83e89,0x3f6fbf77,
0x3e60bea1,0x3f7abf73,0xbf093ee6,0x3f58bf65,0x3cc9bdfb,0x3f80bf7e,0xbf313f1d,0x3f39bf4a,0x3f803f80,0xbf353f35,0x3f803f80,0xbf353f35,
0x3f803f80,0xbf353f35,0x3f803f80,0xbf353f35,0x3f803f80,0xbf353f35,0x3f803f80,0xbf353f35,0x3f803f80,0xbf353f35,0x3f803f80,0xbf353f35,
0xbe2fbd97,0xbf7cbf7f,0xbf51bf42,0xbf13bf27,0xbeb8be89,0xbf6fbf77,0xbf6abf5f,0xbecfbefc,0xbf09bee6,0xbf58bf65,0xbf7abf73,0xbe60bea1,
0xbf31bf1d,0xbf39bf4a,0xbf80bf7e,0xbcc9bdfb,0xbf71bf7d,0x3eac3e16,0x3eac3e16,0x3f713f7d,0xbf3ebf5c,0x3f2c3f04,0x3f2c3f04,0x3f3e3f5c,
0xbedbbf18,0x3f673f4e,0x3f673f4e,0x3edb3f18,0xbd49be79,0x3f803f78,0x3f803f78,0x3d493e79,0x3efc3e60,0x3f5f3f7a,0x3e893f09,0xbf77bf58,
0x3f653f39,0x3ee63f31,0xbea1bcc9,0xbf73bf80,0x3f7e3f7c,0xbdfb3e2f,0xbf4abf13,0xbf1dbf51,0x3f423f6a,0xbf27becf,0xbf7fbf6f,0xbd97beb8,
0x3f463f75,0xbf22be95,0xbf46bf75,0x3f223e95,0x3dc93ef1,0xbf7fbf62,0xbdc9bef1,0x3f7f3f62,0xbf22be95,0xbf46bf75,0x3f223e95,0x3f463f75,
0xbf7fbf62,0xbdc9bef1,0x3f7f3f62,0x3dc93ef1,0xbf42beb8,0xbf27bf6f,0x3f7f3f6a,0xbd973ecf,0xbf77bf7a,0x3e89be60,0x3efc3f58,0xbf5fbf09,
0xbea1bf39,0x3f733f31,0xbee63cc9,0xbf65bf80,0x3f1d3e2f,0x3f4a3f7c,0xbf7ebf51,0xbdfbbf13,0xbf04bf67,0x3f5c3edb,0xbf5cbedb,0xbf04bf67,
0x3f183d49,0x3f4e3f80,0xbf4ebf80,0x3f183d49,0x3f783f71,0xbe793eac,0x3e79beac,0x3f783f71,0x3e163f2c,0xbf7dbf3e,0x3f7d3f3e,0x3e163f2c,
0x3f6f3efc,0x3eb83f5f,0x3ecfbe89,0x3f6a3f77,0x3f093f73,0xbf58bea1,0x3f7a3f65,0xbe603ee6,0xbf39bdfb,0xbf31bf7e,0xbcc93f1d,0xbf80bf4a,
0xbf51bf7f,0x3f13bd97,0xbf7cbf27,0xbe2fbf42,0x3e483f55,0xbf7bbf0e,0x3e483f55,0xbf7bbf0e,0xbf7bbf0e,0xbe48bf55,0xbf7bbf0e,0xbe48bf55,
0xbe48bf55,0x3f7b3f0e,0xbe48bf55,0x3f7b3f0e,0x3f7b3f0e,0x3e483f55,0x3f7b3f0e,0x3e483f55,0xbf80bf1d,0xbcc9bf4a,0xbf39bf7e,0x3f31bdfb,
0x3e2fbf27,0x3f7c3f42,0x3f513d97,0x3f133f7f,0x3f6f3f5f,0xbeb83efc,0x3ecf3f77,0xbf6abe89,0xbf093ea1,0xbf58bf73,0xbf7abee6,0xbe60bf65,
0x3e16bf3e,0x3f7d3f2c,0x3f7d3f2c,0xbe163f3e,0x3f5c3f67,0xbf043edb,0xbf043edb,0xbf5cbf67,0xbf4e3d49,0xbf18bf80,0xbf18bf80,0x3f4ebd49,
0xbe79bf71,0x3f783eac,0x3f783eac,0x3e793f71,0x3f733f39,0xbea13f31,0xbf65bcc9,0xbee6bf80,0xbf4a3e2f,0xbf1dbf7c,0x3dfbbf51,0x3f7e3f13,
0xbd97bf6a,0x3f7f3ecf,0x3f423f6f,0xbf273eb8,0x3f5f3f58,0xbefc3f09,0xbf77be60,0xbe89bf7a,0xbef13f22,0xbf62bf46,0x3ef1bf22,0x3f623f46,
0xbe95bf7f,0x3f753dc9,0x3e953f7f,0xbf75bdc9,0x3f623f46,0xbef13f22,0xbf62bf46,0x3ef1bf22,0xbf75bdc9,0xbe95bf7f,0x3f753dc9,0x3e953f7f,
0xbf4abf51,0x3f1dbf13,0x3dfb3f7c,0xbf7ebe2f,0x3f7f3eb8,0xbd973f6f,0xbf27bf6a,0x3f42becf,0xbf5f3e60,0xbefcbf7a,0x3f773f09,0xbe893f58,
0x3ee6bf39,0x3f653f31,0xbf733cc9,0xbea1bf80,0x3f3ebf04,0x3f2c3f5c,0xbf2cbf5c,0x3f3ebf04,0xbedb3f4e,0xbf67bf18,0x3f673f18,0xbedb3f4e,
0x3d49bf78,0x3f803e79,0xbf80be79,0x3d49bf78,0x3eac3f7d,0xbf713e16,0x3f71be16,0x3eac3f7d,0x3f093f65,0xbf583ee6,0x3f7a3ea1,0xbe603f73,
0xbf31bf4a,0x3f39bf1d,0xbf80bdfb,0x3cc9bf7e,0x3f513f27,0xbf133f42,0x3f7cbd97,0x3e2f3f7f,0xbf6abefc,0x3ecfbf5f,0xbf6f3e89,0xbeb8bf77,
0xbf6d3ec4,0xbec4bf6d,0xbf6d3ec4,0xbec4bf6d,0x3f6dbec4,0x3ec43f6d,0x3f6dbec4,0x3ec43f6d,0xbf6d3ec4,0xbec4bf6d,0xbf6d3ec4,0xbec4bf6d,
0x3f6dbec4,0x3ec43f6d,0x3f6dbec4,0x3ec43f6d,0xbe60bf73,0x3f7abea1,0x3f09bf65,0x3f583ee6,0x3cc93f7e,0xbf803dfb,0xbf313f4a,0xbf39bf1d,
0x3e2fbf7f,0x3f7c3d97,0x3f51bf27,0x3f133f42,0xbeb83f77,0xbf6fbe89,0xbf6a3efc,0xbecfbf5f,0x3f80be79,0x3d493f78,0x3d493f78,0xbf803e79,
0xbf71be16,0x3eacbf7d,0x3eacbf7d,0x3f713e16,0x3f3e3f04,0xbf2c3f5c,0xbf2c3f5c,0xbf3ebf04,0xbedbbf4e,0x3f67bf18,0x3f67bf18,0x3edb3f4e,
0xbdfb3f7c,0xbf7e3e2f,0xbf1dbf13,0x3f4abf51,0x3f27bf6a,0x3f423ecf,0x3d973f6f,0xbf7f3eb8,0xbf773f09,0xbe89bf58,0x3efcbf7a,0x3f5f3e60,
0x3f733cc9,0xbea13f80,0xbf653f31,0xbee6bf39,0xbf753dc9,0x3e95bf7f,0x3f75bdc9,0xbe953f7f,0x3ef13f22,0xbf623f46,0xbef1bf22,0x3f62bf46,
0x3e95bf7f,0x3f75bdc9,0xbe953f7f,0xbf753dc9,0xbf623f46,0xbef1bf22,0x3f62bf46,0x3ef13f22,0x3ee6bf80,0x3f65bcc9,0xbf733f39,0xbea1bf31,
0xbf7e3f13,0xbdfbbf51,0x3f4a3e2f,0xbf1d3f7c,0x3f273eb8,0xbf423f6f,0x3d97bf6a,0x3f7fbecf,0x3e89bf7a,0x3f77be60,0xbf5f3f58,0xbefcbf09,
0x3f4e3d49,0xbf183f80,0x3f18bf80,0x3f4e3d49,0x3e79bf71,0x3f78beac,0xbf783eac,0x3e79bf71,0xbf7d3f2c,0xbe16bf3e,0x3e163f3e,0xbf7d3f2c,
0x3f043edb,0xbf5c3f67,0x3f5cbf67,0x3f043edb,0xbf393f7e,0xbf31bdfb,0xbcc93f4a,0xbf803f1d,0x3f51bd97,0xbf133f7f,0x3f7cbf42,0x3e2f3f27,
0x3ecfbf77,0x3f6abe89,0xbeb8befc,0x3f6fbf5f,0xbf7a3ee6,0x3e60bf65,0xbf583f73,0xbf09bea1,0xbf0ebe48,0x3f55bf7b,0xbf0ebe48,0x3f55bf7b,
0xbf553f7b,0xbf0ebe48,0xbf553f7b,0xbf0ebe48,0x3f0e3e48,0xbf553f7b,0x3f0e3e48,0xbf553f7b,0x3f55bf7b,0x3f0e3e48,0x3f55bf7b,0x3f0e3e48,
0x3f6abf77,0x3ecf3e89,0x3f6fbefc,0xbeb83f5f,0xbe60bee6,0x3f7abf65,0x3f09bf73,0x3f58bea1,0xbf803f4a,0xbcc9bf1d,0xbf393dfb,0x3f31bf7e,
0xbe2f3f42,0xbf7c3f27,0xbf513f7f,0xbf13bd97,0x3e793eac,0xbf783f71,0xbf783f71,0xbe79beac,0x3f7dbf3e,0xbe163f2c,0xbe163f2c,0xbf7d3f3e,
0x3f04bf67,0x3f5cbedb,0x3f5cbedb,0xbf043f67,0xbf183d49,0x3f4ebf80,0x3f4ebf80,0x3f18bd49,0xbf7f3f6a,0xbd97becf,0x3f27bf6f,0x3f42beb8,
0xbefc3f58,0xbf5f3f09,0xbe89be60,0x3f77bf7a,0x3ee63cc9,0xbf653f80,0xbf733f31,0x3ea1bf39,0x3f7ebf51,0xbdfb3f13,0xbf4a3f7c,0xbf1d3e2f,
0x3dc9bef1,0x3f7fbf62,0xbdc93ef1,0xbf7f3f62,0xbf223e95,0x3f46bf75,0x3f22be95,0xbf463f75,0xbf7f3f62,0x3dc9bef1,0x3f7fbf62,0xbdc93ef1,
0xbf463f75,0xbf223e95,0x3f46bf75,0x3f22be95,0x3f77bf58,0xbe893f09,0xbefc3e60,0x3f5fbf7a,0x3f73bf80,0x3ea1bcc9,0xbf653f39,0x3ee6bf31,
0x3f1dbf51,0x3f4abf13,0xbf7e3f7c,0xbdfbbe2f,0x3d97beb8,0x3f7fbf6f,0xbf423f6a,0xbf273ecf,0xbedb3f18,0xbf673f4e,0x3f67bf4e,0xbedb3f18,
0xbd493e79,0xbf803f78,0x3f80bf78,0xbd493e79,0x3eacbe16,0xbf713f7d,0x3f71bf7d,0x3eacbe16,0x3f2cbf04,0xbf3e3f5c,0x3f3ebf5c,0x3f2cbf04,
0xbf513f42,0x3f13bf27,0xbf7c3f7f,0xbe2f3d97,0xbf6a3f5f,0x3ecfbefc,0xbf6f3f77,0xbeb83e89,0xbf7a3f73,0x3e60bea1,0xbf583f65,0xbf093ee6,
0xbf803f7e,0x3cc9bdfb,0xbf393f4a,0xbf313f1d,0x3f803f80,0xbf353f35,0x3f803f80,0xbf353f35,0x3f803f80,0xbf353f35,0x3f803f80,0xbf353f35,
0x3f803f80,0xbf353f35,0x3f803f80,0xbf353f35,0x3f803f80,0xbf353f35,0x3f803f80,0xbf353f35,0xbf7cbf7f,0x3e2f3d97,0xbf13bf27,0x3f513f42,
0xbf6fbf77,0x3eb83e89,0xbecfbefc,0x3f6a3f5f,0xbf58bf65,0x3f093ee6,0xbe60bea1,0x3f7a3f73,0xbf39bf4a,0x3f313f1d,0xbcc9bdfb,0x3f803f7e,
0x3f713f7d,0xbeacbe16,0xbeacbe16,0xbf71bf7d,0x3f3e3f5c,0xbf2cbf04,0xbf2cbf04,0xbf3ebf5c,0x3edb3f18,0xbf67bf4e,0xbf67bf4e,0xbedbbf18,
0x3d493e79,0xbf80bf78,0xbf80bf78,0xbd49be79,0xbf5fbf7a,0x3efc3e60,0x3f773f58,0x3e893f09,0xbee6bf31,0x3f653f39,0x3f733f80,0xbea1bcc9,
0x3dfbbe2f,0x3f7e3f7c,0x3f1d3f51,0xbf4abf13,0x3f273ecf,0x3f423f6a,0x3d973eb8,0xbf7fbf6f,0x3f463f75,0xbf22be95,0xbf46bf75,0x3f223e95,
0x3dc93ef1,0xbf7fbf62,0xbdc9bef1,0x3f7f3f62,0xbf22be95,0xbf46bf75,0x3f223e95,0x3f463f75,0xbf7fbf62,0xbdc9bef1,0x3f7f3f62,0x3dc93ef1,
0xbf27bf6f,0x3f423eb8,0xbd973ecf,0xbf7fbf6a,0x3e89be60,0x3f773f7a,0xbf5fbf09,0xbefcbf58,0x3f733f31,0x3ea13f39,0xbf65bf80,0x3ee6bcc9,
0x3f4a3f7c,0xbf1dbe2f,0xbdfbbf13,0x3f7e3f51,0x3f043f67,0xbf5cbedb,0x3f5c3edb,0x3f043f67,0xbf18bd49,0xbf4ebf80,0x3f4e3f80,0xbf18bd49,
0xbf78bf71,0x3e79beac,0xbe793eac,0xbf78bf71,0xbe16bf2c,0x3f7d3f3e,0xbf7dbf3e,0xbe16bf2c,0xbeb8bf5f,0x3f6f3efc,0xbf6abf77,0x3ecfbe89,
0x3f583ea1,0x3f093f73,0x3e60bee6,0x3f7a3f65,0x3f313f7e,0xbf39bdfb,0x3f803f4a,0xbcc93f1d,0xbf133d97,0xbf51bf7f,0x3e2f3f42,0xbf7cbf27,
0x3e483f55,0xbf7bbf0e,0x3e483f55,0xbf7bbf0e,0xbf7bbf0e,0xbe48bf55,0xbf7bbf0e,0xbe48bf55,0xbe48bf55,0x3f7b3f0e,0xbe48bf55,0x3f7b3f0e,
0x3f7b3f0e,0x3e483f55,0x3f7b3f0e,0x3e483f55,0xbcc9bf4a,0x3f803f1d,0x3f31bdfb,0x3f393f7e,0x3f7c3f42,0xbe2f3f27,0x3f133f7f,0xbf51bd97,
0xbeb83efc,0xbf6fbf5f,0xbf6abe89,0xbecfbf77,0xbf58bf73,0x3f09bea1,0xbe60bf65,0x3f7a3ee6,0xbe163f3e,0xbf7dbf2c,0xbf7dbf2c,0x3e16bf3e,
0xbf5cbf67,0x3f04bedb,0x3f04bedb,0x3f5c3f67,0x3f4ebd49,0x3f183f80,0x3f183f80,0xbf4e3d49,0x3e793f71,0xbf78beac,0xbf78beac,0xbe79bf71,
0x3ea1bf31,0x3f733f39,0x3ee63f80,0xbf65bcc9,0x3f1d3f7c,0xbf4a3e2f,0xbf7ebf13,0x3dfbbf51,0xbf7fbecf,0xbd97bf6a,0x3f27beb8,0x3f423f6f,
0x3efcbf09,0x3f5f3f58,0x3e893f7a,0xbf77be60,0xbef13f22,0xbf62bf46,0x3ef1bf22,0x3f623f46,0xbe95bf7f,0x3f753dc9,0x3e953f7f,0xbf75bdc9,
0x3f623f46,0xbef13f22,0xbf62bf46,0x3ef1bf22,0xbf75bdc9,0xbe95bf7f,0x3f753dc9,0x3e953f7f,0x3f1dbf13,0x3f4a3f51,0xbf7ebe2f,0xbdfbbf7c,
0xbd973f6f,0xbf7fbeb8,0x3f42becf,0x3f273f6a,0xbefcbf7a,0x3f5fbe60,0xbe893f58,0xbf77bf09,0x3f653f31,0xbee63f39,0xbea1bf80,0x3f73bcc9,
0xbf3e3f04,0xbf2cbf5c,0x3f2c3f5c,0xbf3e3f04,0x3edbbf4e,0x3f673f18,0xbf67bf18,0x3edbbf4e,0xbd493f78,0xbf80be79,0x3f803e79,0xbd493f78,
0xbeacbf7d,0x3f71be16,0xbf713e16,0xbeacbf7d,0x3f58bee6,0x3f093f65,0x3e60bf73,0x3f7a3ea1,0xbf393f1d,0xbf31bf4a,0xbcc93f7e,0xbf80bdfb,
0x3f13bf42,0x3f513f27,0xbe2fbf7f,0x3f7cbd97,0xbecf3f5f,0xbf6abefc,0x3eb83f77,0xbf6f3e89,0xbf6d3ec4,0xbec4bf6d,0xbf6d3ec4,0xbec4bf6d,
0x3f6dbec4,0x3ec43f6d,0x3f6dbec4,0x3ec43f6d,0xbf6d3ec4,0xbec4bf6d,0xbf6d3ec4,0xbec4bf6d,0x3f6dbec4,0x3ec43f6d,0x3f6dbec4,0x3ec43f6d,
0x3f7abea1,0x3e603f73,0x3f583ee6,0xbf093f65,0xbf803dfb,0xbcc9bf7e,0xbf39bf1d,0x3f31bf4a,0x3f7c3d97,0xbe2f3f7f,0x3f133f42,0xbf513f27,
0xbf6fbe89,0x3eb8bf77,0xbecfbf5f,0x3f6abefc,0xbf803e79,0xbd49bf78,0xbd49bf78,0x3f80be79,0x3f713e16,0xbeac3f7d,0xbeac3f7d,0xbf71be16,
0xbf3ebf04,0x3f2cbf5c,0x3f2cbf5c,0x3f3e3f04,0x3edb3f4e,0xbf673f18,0xbf673f18,0xbedbbf4e,0x3f7ebe2f,0xbdfb3f7c,0xbf4a3f51,0xbf1dbf13,
0xbf42becf,0x3f27bf6a,0x3f7fbeb8,0x3d973f6f,0x3e893f58,0xbf773f09,0xbf5fbe60,0x3efcbf7a,0x3ea1bf80,0x3f733cc9,0x3ee63f39,0xbf653f31,
0xbf753dc9,0x3e95bf7f,0x3f75bdc9,0xbe953f7f,0x3ef13f22,0xbf623f46,0xbef1bf22,0x3f62bf46,0x3e95bf7f,0x3f75bdc9,0xbe953f7f,0xbf753dc9,
0xbf623f46,0xbef1bf22,0x3f62bf46,0x3ef13f22,0x3f65bcc9,0xbee63f80,0xbea1bf31,0x3f73bf39,0xbdfbbf51,0x3f7ebf13,0xbf1d3f7c,0xbf4abe2f,
0xbf423f6f,0xbf27beb8,0x3f7fbecf,0xbd973f6a,0x3f77be60,0xbe893f7a,0xbefcbf09,0x3f5fbf58,0xbf4ebd49,0x3f18bf80,0xbf183f80,0xbf4ebd49,
0xbe793f71,0xbf783eac,0x3f78beac,0xbe793f71,0x3f7dbf2c,0x3e163f3e,0xbe16bf3e,0x3f7dbf2c,0xbf04bedb,0x3f5cbf67,0xbf5c3f67,0xbf04bedb,
0x3f313dfb,0xbf393f7e,0x3f80bf1d,0xbcc93f4a,0x3f13bf7f,0x3f51bd97,0xbe2fbf27,0x3f7cbf42,0xbf6a3e89,0x3ecfbf77,0xbf6f3f5f,0xbeb8befc,
0xbe603f65,0xbf7a3ee6,0x3f093ea1,0xbf583f73,0xbf0ebe48,0x3f55bf7b,0xbf0ebe48,0x3f55bf7b,0xbf553f7b,0xbf0ebe48,0xbf553f7b,0xbf0ebe48,
0x3f0e3e48,0xbf553f7b,0x3f0e3e48,0xbf553f7b,0x3f55bf7b,0x3f0e3e48,0x3f55bf7b,0x3f0e3e48,0x3ecf3e89,0xbf6a3f77,0xbeb83f5f,0xbf6f3efc,
0x3f7abf65,0x3e603ee6,0x3f58bea1,0xbf093f73,0xbcc9bf1d,0x3f80bf4a,0x3f31bf7e,0x3f39bdfb,0xbf7c3f27,0x3e2fbf42,0xbf13bd97,0x3f51bf7f,
0xbe79beac,0x3f78bf71,0x3f78bf71,0x3e793eac,0xbf7d3f3e,0x3e16bf2c,0x3e16bf2c,0x3f7dbf3e,0xbf043f67,0xbf5c3edb,0xbf5c3edb,0x3f04bf67,
0x3f18bd49,0xbf4e3f80,0xbf4e3f80,0xbf183d49,0x3d973ecf,0xbf7f3f6a,0xbf423eb8,0x3f27bf6f,0x3f5fbf09,0xbefc3f58,0xbf773f7a,0xbe89be60,
0x3f65bf80,0x3ee63cc9,0xbea13f39,0xbf733f31,0x3dfbbf13,0x3f7ebf51,0x3f1dbe2f,0xbf4a3f7c,0x3dc9bef1,0x3f7fbf62,0xbdc93ef1,0xbf7f3f62,
0xbf223e95,0x3f46bf75,0x3f22be95,0xbf463f75,0xbf7f3f62,0x3dc9bef1,0x3f7fbf62,0xbdc93ef1,0xbf463f75,0xbf223e95,0x3f46bf75,0x3f22be95,
0xbe893f09,0xbf773f58,0x3f5fbf7a,0x3efcbe60,0x3ea1bcc9,0xbf733f80,0x3ee6bf31,0x3f65bf39,0x3f4abf13,0xbf1d3f51,0xbdfbbe2f,0x3f7ebf7c,
0x3f7fbf6f,0xbd973eb8,0xbf273ecf,0x3f42bf6a,0x3edbbf18,0x3f67bf4e,0xbf673f4e,0x3edbbf18,0x3d49be79,0x3f80bf78,0xbf803f78,0x3d49be79,
0xbeac3e16,0x3f71bf7d,0xbf713f7d,0xbeac3e16,0xbf2c3f04,0x3f3ebf5c,0xbf3e3f5c,0xbf2c3f04,0xbf133f27,0xbf513f42,0x3e2fbd97,0xbf7c3f7f,
0xbecf3efc,0xbf6a3f5f,0x3eb8be89,0xbf6f3f77,0xbe603ea1,0xbf7a3f73,0x3f09bee6,0xbf583f65,0xbcc93dfb,0xbf803f7e,0x3f31bf1d,0xbf393f4a,
0x3f803f80,0xbf353f35,0x3f803f80,0xbf353f35,0x3f803f80,0xbf353f35,0x3f803f80,0xbf353f35,0x3f803f80,0xbf353f35,0x3f803f80,0xbf353f35,
0x3f803f80,0xbf353f35,0x3f803f80,0xbf353f35,0x3e2f3d97,0x3f7c3f7f,0x3f513f42,0x3f133f27,0x3eb83e89,0x3f6f3f77,0x3f6a3f5f,0x3ecf3efc,
0x3f093ee6,0x3f583f65,0x3f7a3f73,0x3e603ea1,0x3f313f1d,0x3f393f4a,0x3f803f7e,0x3cc93dfb,0xbf71bf7d,0x3eac3e16,0x3eac3e16,0x3f713f7d,
0xbf3ebf5c,0x3f2c3f04,0x3f2c3f04,0x3f3e3f5c,0xbedbbf18,0x3f673f4e,0x3f673f4e,0x3edb3f18,0xbd49be79,0x3f803f78,0x3f803f78,0x3d493e79,
0xbefcbe60,0xbf5fbf7a,0xbe89bf09,0x3f773f58,0xbf65bf39,0xbee6bf31,0x3ea13cc9,0x3f733f80,0xbf7ebf7c,0x3dfbbe2f,0x3f4a3f13,0x3f1d3f51,
0xbf42bf6a,0x3f273ecf,0x3f7f3f6f,0x3d973eb8,0x3f463f75,0xbf22be95,0xbf46bf75,0x3f223e95,0x3dc93ef1,0xbf7fbf62,0xbdc9bef1,0x3f7f3f62,
0xbf22be95,0xbf46bf75,0x3f223e95,0x3f463f75,0xbf7fbf62,0xbdc9bef1,0x3f7f3f62,0x3dc93ef1,0x3f423eb8,0x3f273f6f,0xbf7fbf6a,0x3d97becf,
0x3f773f7a,0xbe893e60,0xbefcbf58,0x3f5f3f09,0x3ea13f39,0xbf73bf31,0x3ee6bcc9,0x3f653f80,0xbf1dbe2f,0xbf4abf7c,0x3f7e3f51,0x3dfb3f13,
0xbf04bf67,0x3f5c3edb,0xbf5cbedb,0xbf04bf67,0x3f183d49,0x3f4e3f80,0xbf4ebf80,0x3f183d49,0x3f783f71,0xbe793eac,0x3e79beac,0x3f783f71,
0x3e163f2c,0xbf7dbf3e,0x3f7d3f3e,0x3e163f2c,0xbf6fbefc,0xbeb8bf5f,0xbecf3e89,0xbf6abf77,0xbf09bf73,0x3f583ea1,0xbf7abf65,0x3e60bee6,
0x3f393dfb,0x3f313f7e,0x3cc9bf1d,0x3f803f4a,0x3f513f7f,0xbf133d97,0x3f7c3f27,0x3e2f3f42,0x3e483f55,0xbf7bbf0e,0x3e483f55,0xbf7bbf0e,
0xbf7bbf0e,0xbe48bf55,0xbf7bbf0e,0xbe48bf55,0xbe48bf55,0x3f7b3f0e,0xbe48bf55,0x3f7b3f0e,0x3f7b3f0e,0x3e483f55,0x3f7b3f0e,0x3e483f55,
0x3f803f1d,0x3cc93f4a,0x3f393f7e,0xbf313dfb,0xbe2f3f27,0xbf7cbf42,0xbf51bd97,0xbf13bf7f,0xbf6fbf5f,0x3eb8befc,0xbecfbf77,0x3f6a3e89,
0x3f09bea1,0x3f583f73,0x3f7a3ee6,0x3e603f65,0x3e16bf3e,0x3f7d3f2c,0x3f7d3f2c,0xbe163f3e,0x3f5c3f67,0xbf043edb,0xbf043edb,0xbf5cbf67,
0xbf4e3d49,0xbf18bf80,0xbf18bf80,0x3f4ebd49,0xbe79bf71,0x3f783eac,0x3f783eac,0x3e793f71,0xbf73bf39,0x3ea1bf31,0x3f653cc9,0x3ee63f80,
0x3f4abe2f,0x3f1d3f7c,0xbdfb3f51,0xbf7ebf13,0x3d973f6a,0xbf7fbecf,0xbf42bf6f,0x3f27beb8,0xbf5fbf58,0x3efcbf09,0x3f773e60,0x3e893f7a,
0xbef13f22,0xbf62bf46,0x3ef1bf22,0x3f623f46,0xbe95bf7f,0x3f753dc9,0x3e953f7f,0xbf75bdc9,0x3f623f46,0xbef13f22,0xbf62bf46,0x3ef1bf22,
0xbf75bdc9,0xbe95bf7f,0x3f753dc9,0x3e953f7f,0x3f4a3f51,0xbf1d3f13,0xbdfbbf7c,0x3f7e3e2f,0xbf7fbeb8,0x3d97bf6f,0x3f273f6a,0xbf423ecf,
0x3f5fbe60,0x3efc3f7a,0xbf77bf09,0x3e89bf58,0xbee63f39,0xbf65bf31,0x3f73bcc9,0x3ea13f80,0x3f3ebf04,0x3f2c3f5c,0xbf2cbf5c,0x3f3ebf04,
0xbedb3f4e,0xbf67bf18,0x3f673f18,0xbedb3f4e,0x3d49bf78,0x3f803e79,0xbf80be79,0x3d49bf78,0x3eac3f7d,0xbf713e16,0x3f71be16,0x3eac3f7d,
0xbf09bf65,0x3f58bee6,0xbf7abea1,0x3e60bf73,0x3f313f4a,0xbf393f1d,0x3f803dfb,0xbcc93f7e,0xbf51bf27,0x3f13bf42,0xbf7c3d97,0xbe2fbf7f,
0x3f6a3efc,0xbecf3f5f,0x3f6fbe89,0x3eb83f77,0xbf6d3ec4,0xbec4bf6d,0xbf6d3ec4,0xbec4bf6d,0x3f6dbec4,0x3ec43f6d,0x3f6dbec4,0x3ec43f6d,
0xbf6d3ec4,0xbec4bf6d,0xbf6d3ec4,0xbec4bf6d,0x3f6dbec4,0x3ec43f6d,0x3f6dbec4,0x3ec43f6d,0x3e603f73,0xbf7a3ea1,0xbf093f65,0xbf58bee6,
0xbcc9bf7e,0x3f80bdfb,0x3f31bf4a,0x3f393f1d,0xbe2f3f7f,0xbf7cbd97,0xbf513f27,0xbf13bf42,0x3eb8bf77,0x3f6f3e89,0x3f6abefc,0x3ecf3f5f,
0x3f80be79,0x3d493f78,0x3d493f78,0xbf803e79,0xbf71be16,0x3eacbf7d,0x3eacbf7d,0x3f713e16,0x3f3e3f04,0xbf2c3f5c,0xbf2c3f5c,0xbf3ebf04,
0xbedbbf4e,0x3f67bf18,0x3f67bf18,0x3edb3f4e,0x3dfbbf7c,0x3f7ebe2f,0x3f1d3f13,0xbf4a3f51,0xbf273f6a,0xbf42becf,0xbd97bf6f,0x3f7fbeb8,
0x3f77bf09,0x3e893f58,0xbefc3f7a,0xbf5fbe60,0xbf73bcc9,0x3ea1bf80,0x3f65bf31,0x3ee63f39,0xbf753dc9,0x3e95bf7f,0x3f75bdc9,0xbe953f7f,
0x3ef13f22,0xbf623f46,0xbef1bf22,0x3f62bf46,0x3e95bf7f,0x3f75bdc9,0xbe953f7f,0xbf753dc9,0xbf623f46,0xbef1bf22,0x3f62bf46,0x3ef13f22,
0xbee63f80,0xbf653cc9,0x3f73bf39,0x3ea13f31,0x3f7ebf13,0x3dfb3f51,0xbf4abe2f,0x3f1dbf7c,0xbf27beb8,0x3f42bf6f,0xbd973f6a,0xbf7f3ecf,
0xbe893f7a,0xbf773e60,0x3f5fbf58,0x3efc3f09,0x3f4e3d49,0xbf183f80,0x3f18bf80,0x3f4e3d49,0x3e79bf71,0x3f78beac,0xbf783eac,0x3e79bf71,
0xbf7d3f2c,0xbe16bf3e,0x3e163f3e,0xbf7d3f2c,0x3f043edb,0xbf5c3f67,0x3f5cbf67,0x3f043edb,0x3f39bf7e,0x3f313dfb,0x3cc9bf4a,0x3f80bf1d,
0xbf513d97,0x3f13bf7f,0xbf7c3f42,0xbe2fbf27,0xbecf3f77,0xbf6a3e89,0x3eb83efc,0xbf6f3f5f,0x3f7abee6,0xbe603f65,0x3f58bf73,0x3f093ea1,
0xbf0ebe48,0x3f55bf7b,0xbf0ebe48,0x3f55bf7b,0xbf553f7b,0xbf0ebe48,0xbf553f7b,0xbf0ebe48,0x3f0e3e48,0xbf553f7b,0x3f0e3e48,0xbf553f7b,
0x3f55bf7b,0x3f0e3e48,0x3f55bf7b,0x3f0e3e48,0xbf6a3f77,0xbecfbe89,0xbf6f3efc,0x3eb8bf5f,0x3e603ee6,0xbf7a3f65,0xbf093f73,0xbf583ea1,
0x3f80bf4a,0x3cc93f1d,0x3f39bdfb,0xbf313f7e,0x3e2fbf42,0x3f7cbf27,0x3f51bf7f,0x3f133d97,0x3e793eac,0xbf783f71,0xbf783f71,0xbe79beac,
0x3f7dbf3e,0xbe163f2c,0xbe163f2c,0xbf7d3f3e,0x3f04bf67,0x3f5cbedb,0x3f5cbedb,0xbf043f67,0xbf183d49,0x3f4ebf80,0x3f4ebf80,0x3f18bd49,
0x3f7fbf6a,0x3d973ecf,0xbf273f6f,0xbf423eb8,0x3efcbf58,0x3f5fbf09,0x3e893e60,0xbf773f7a,0xbee6bcc9,0x3f65bf80,0x3f73bf31,0xbea13f39,
0xbf7e3f51,0x3dfbbf13,0x3f4abf7c,0x3f1dbe2f,0x3dc9bef1,0x3f7fbf62,0xbdc93ef1,0xbf7f3f62,0xbf223e95,0x3f46bf75,0x3f22be95,0xbf463f75,
0xbf7f3f62,0x3dc9bef1,0x3f7fbf62,0xbdc93ef1,0xbf463f75,0xbf223e95,0x3f46bf75,0x3f22be95,0xbf773f58,0x3e89bf09,0x3efcbe60,0xbf5f3f7a,
0xbf733f80,0xbea13cc9,0x3f65bf39,0xbee63f31,0xbf1d3f51,0xbf4a3f13,0x3f7ebf7c,0x3dfb3e2f,0xbd973eb8,0xbf7f3f6f,0x3f42bf6a,0x3f27becf,
0xbedb3f18,0xbf673f4e,0x3f67bf4e,0xbedb3f18,0xbd493e79,0xbf803f78,0x3f80bf78,0xbd493e79,0x3eacbe16,0xbf713f7d,0x3f71bf7d,0x3eacbe16,
0x3f2cbf04,0xbf3e3f5c,0x3f3ebf5c,0x3f2cbf04,0x3f51bf42,0xbf133f27,0x3f7cbf7f,0x3e2fbd97,0x3f6abf5f,0xbecf3efc,0x3f6fbf77,0x3eb8be89,
0x3f7abf73,0xbe603ea1,0x3f58bf65,0x3f09bee6,0x3f80bf7e,0xbcc93dfb,0x3f39bf4a,0x3f31bf1d,0x3f803f80,0x3f803f80,0x3f803f80,0x3f803f80,
0x0,0x0,0x0,0x0,0x3f803f80,0x3f803f80,0x3f803f80,0x3f803f80,0x0,0x0,0x0,0x0,
0x3f803f80,0x3f803f80,0x3f803f80,0x3f803f80,0x0,0x0,0x0,0x0,0x3f803f80,0x3f803f80,0x3f803f80,0x3f803f80,
0x0,0x0,0x0,0x0,0x3e480000,0x3f0e3ec4,0x3f553f35,0x3f7b3f6d,0x3f7b3f80,0x3f553f6d,0x3f0e3f35,0x3e483ec4,
0x3f7b3f80,0x3f553f6d,0x3f0e3f35,0x3e483ec4,0xbe480000,0xbf0ebec4,0xbf55bf35,0xbf7bbf6d,0xbe480000,0xbf0ebec4,0xbf55bf35,0xbf7bbf6d,
0xbf7bbf80,0xbf55bf6d,0xbf0ebf35,0xbe48bec4,0xbf7bbf80,0xbf55bf6d,0xbf0ebf35,0xbe48bec4,0x3e480000,0x3f0e3ec4,0x3f553f35,0x3f7b3f6d,
0xbf6dbf80,0xbec4bf35,0x3ec40000,0x3f6d3f35,0xbec40000,0xbf6dbf35,0xbf6dbf80,0xbec4bf35,0x3f6d3f80,0x3ec43f35,0xbec40000,0xbf6dbf35,
0x3ec40000,0x3f6d3f35,0x3f6d3f80,0x3ec43f35,0xbf6dbf80,0xbec4bf35,0x3ec40000,0x3f6d3f35,0xbec40000,0xbf6dbf35,0xbf6dbf80,0xbec4bf35,
0x3f6d3f80,0x3ec43f35,0xbec40000,0xbf6dbf35,0x3ec40000,0x3f6d3f35,0x3f6d3f80,0x3ec43f35,0xbf55bf80,0x3e48bec4,0x3f7b3f35,0x3f0e3f6d,
0x3f0e0000,0x3f7b3f6d,0x3e483f35,0xbf55bec4,0x3f0e0000,0x3f7b3f6d,0x3e483f35,0xbf55bec4,0x3f553f80,0xbe483ec4,0xbf7bbf35,0xbf0ebf6d,
0x3f553f80,0xbe483ec4,0xbf7bbf35,0xbf0ebf6d,0xbf0e0000,0xbf7bbf6d,0xbe48bf35,0x3f553ec4,0xbf0e0000,0xbf7bbf6d,0xbe48bf35,0x3f553ec4,
0xbf55bf80,0x3e48bec4,0x3f7b3f35,0x3f0e3f6d,0x3f353f80,0xbf350000,0xbf35bf80,0x3f350000,0x3f350000,0x3f353f80,0xbf350000,0xbf35bf80,
0x3f353f80,0xbf350000,0xbf35bf80,0x3f350000,0x3f350000,0x3f353f80,0xbf350000,0xbf35bf80,0x3f353f80,0xbf350000,0xbf35bf80,0x3f350000,
0x3f350000,0x3f353f80,0xbf350000,0xbf35bf80,0x3f353f80,0xbf350000,0xbf35bf80,0x3f350000,0x3f350000,0x3f353f80,0xbf350000,0xbf35bf80,
0xbf550000,0xbe48bf6d,0x3f7b3f35,0xbf0e3ec4,0xbf0ebf80,0x3f7b3ec4,0xbe483f35,0xbf55bf6d,0xbf0ebf80,0x3f7b3ec4,0xbe483f35,0xbf55bf6d,
0x3f550000,0x3e483f6d,0xbf7bbf35,0x3f0ebec4,0x3f550000,0x3e483f6d,0xbf7bbf35,0x3f0ebec4,0x3f0e3f80,0xbf7bbec4,0x3e48bf35,0x3f553f6d,
0x3f0e3f80,0xbf7bbec4,0x3e48bf35,0x3f553f6d,0xbf550000,0xbe48bf6d,0x3f7b3f35,0xbf0e3ec4,0xbec4bf80,0x3f6d3f35,0xbf6d0000,0x3ec4bf35,
0xbf6d0000,0x3ec4bf35,0x3ec43f80,0xbf6dbf35,0x3ec43f80,0xbf6dbf35,0x3f6d0000,0xbec43f35,0x3f6d0000,0xbec43f35,0xbec4bf80,0x3f6d3f35,
0xbec4bf80,0x3f6d3f35,0xbf6d0000,0x3ec4bf35,0xbf6d0000,0x3ec4bf35,0x3ec43f80,0xbf6dbf35,0x3ec43f80,0xbf6dbf35,0x3f6d0000,0xbec43f35,
0x3f6d0000,0xbec43f35,0xbec4bf80,0x3f6d3f35,0x3e483f80,0xbf0ebf6d,0x3f553f35,0xbf7bbec4,0xbf7b0000,0x3f55bec4,0xbf0e3f35,0x3e48bf6d,
0xbf7b0000,0x3f55bec4,0xbf0e3f35,0x3e48bf6d,0xbe48bf80,0x3f0e3f6d,0xbf55bf35,0x3f7b3ec4,0xbe48bf80,0x3f0e3f6d,0xbf55bf35,0x3f7b3ec4,
0x3f7b0000,0xbf553ec4,0x3f0ebf35,0xbe483f6d,0x3f7b0000,0xbf553ec4,0x3f0ebf35,0xbe483f6d,0x3e483f80,0xbf0ebf6d,0x3f553f35,0xbf7bbec4,
0x80008000,0x80008000,0x80008000,0x80008000,0x3f803f80,0x3f803f80,0x3f803f80,0x3f803f80,0x80008000,0x80008000,0x80008000,0x80008000,
0x3f803f80,0x3f803f80,0x3f803f80,0x3f803f80,0x80008000,0x80008000,0x80008000,0x80008000,0x3f803f80,0x3f803f80,0x3f803f80,0x3f803f80,
0x80008000,0x80008000,0x80008000,0x80008000,0x3f803f80,0x3f803f80,0x3f803f80,0x3f803f80,0x3f7b3f80,0x3f553f6d,0x3f0e3f35,0x3e483ec4,
0xbe488000,0xbf0ebec4,0xbf55bf35,0xbf7bbf6d,0xbe480000,0xbf0ebec4,0xbf55bf35,0xbf7bbf6d,0xbf7bbf80,0xbf55bf6d,0xbf0ebf35,0xbe48bec4,
0xbf7bbf80,0xbf55bf6d,0xbf0ebf35,0xbe48bec4,0x3e488000,0x3f0e3ec4,0x3f553f35,0x3f7b3f6d,0x3e480000,0x3f0e3ec4,0x3f553f35,0x3f7b3f6d,
0x3f7b3f80,0x3f553f6d,0x3f0e3f35,0x3e483ec4,0x3ec48000,0x3f6d3f35,0x3f6d3f80,0x3ec43f35,0xbf6dbf80,0xbec4bf35,0x3ec40000,0x3f6d3f35,
0xbec48000,0xbf6dbf35,0xbf6dbf80,0xbec4bf35,0x3f6d3f80,0x3ec43f35,0xbec40000,0xbf6dbf35,0x3ec48000,0x3f6d3f35,0x3f6d3f80,0x3ec43f35,
0xbf6dbf80,0xbec4bf35,0x3ec40000,0x3f6d3f35,0xbec48000,0xbf6dbf35,0xbf6dbf80,0xbec4bf35,0x3f6d3f80,0x3ec43f35,0xbec40000,0xbf6dbf35,
0x3f0e0000,0x3f7b3f6d,0x3e483f35,0xbf55bec4,0x3f553f80,0xbe483ec4,0xbf7bbf35,0xbf0ebf6d,0x3f553f80,0xbe483ec4,0xbf7bbf35,0xbf0ebf6d,
0xbf0e8000,0xbf7bbf6d,0xbe48bf35,0x3f553ec4,0xbf0e0000,0xbf7bbf6d,0xbe48bf35,0x3f553ec4,0xbf55bf80,0x3e48bec4,0x3f7b3f35,0x3f0e3f6d,
0xbf55bf80,0x3e48bec4,0x3f7b3f35,0x3f0e3f6d,0x3f0e8000,0x3f7b3f6d,0x3e483f35,0xbf55bec4,0xbf358000,0xbf35bf80,0x3f358000,0x3f353f80,
0x3f353f80,0xbf350000,0xbf35bf80,0x3f350000,0xbf358000,0xbf35bf80,0x3f358000,0x3f353f80,0x3f353f80,0xbf350000,0xbf35bf80,0x3f350000,
0xbf358000,0xbf35bf80,0x3f358000,0x3f353f80,0x3f353f80,0xbf350000,0xbf35bf80,0x3f350000,0xbf358000,0xbf35bf80,0x3f358000,0x3f353f80,
0x3f353f80,0xbf350000,0xbf35bf80,0x3f350000,0xbf0ebf80,0x3f7b3ec4,0xbe483f35,0xbf55bf6d,0x3f558000,0x3e483f6d,0xbf7bbf35,0x3f0ebec4,
0x3f550000,0x3e483f6d,0xbf7bbf35,0x3f0ebec4,0x3f0e3f80,0xbf7bbec4,0x3e48bf35,0x3f553f6d,0x3f0e3f80,0xbf7bbec4,0x3e48bf35,0x3f553f6d,
0xbf558000,0xbe48bf6d,0x3f7b3f35,0xbf0e3ec4,0xbf550000,0xbe48bf6d,0x3f7b3f35,0xbf0e3ec4,0xbf0ebf80,0x3f7b3ec4,0xbe483f35,0xbf55bf6d,
0x3f6d8000,0xbec43f35,0xbec4bf80,0x3f6d3f35,0xbec4bf80,0x3f6d3f35,0xbf6d0000,0x3ec4bf35,0xbf6d8000,0x3ec4bf35,0x3ec43f80,0xbf6dbf35,
0x3ec43f80,0xbf6dbf35,0x3f6d0000,0xbec43f35,0x3f6d8000,0xbec43f35,0xbec4bf80,0x3f6d3f35,0xbec4bf80,0x3f6d3f35,0xbf6d0000,0x3ec4bf35,
0xbf6d8000,0x3ec4bf35,0x3ec43f80,0xbf6dbf35,0x3ec43f80,0xbf6dbf35,0x3f6d0000,0xbec43f35,0xbf7b0000,0x3f55bec4,0xbf0e3f35,0x3e48bf6d,
0xbe48bf80,0x3f0e3f6d,0xbf55bf35,0x3f7b3ec4,0xbe48bf80,0x3f0e3f6d,0xbf55bf35,0x3f7b3ec4,0x3f7b8000,0xbf553ec4,0x3f0ebf35,0xbe483f6d,
0x3f7b0000,0xbf553ec4,0x3f0ebf35,0xbe483f6d,0x3e483f80,0xbf0ebf6d,0x3f553f35,0xbf7bbec4,0x3e483f80,0xbf0ebf6d,0x3f553f35,0xbf7bbec4,
0xbf7b8000,0x3f55bec4,0xbf0e3f35,0x3e48bf6d,0x3f80,0xbf80,0x3f80,0xbf80,0x3f800000,0xbf800000,0x3f800000,0xbf800000,
0x3f80,0xbf80,0x3f80,0xbf80,0x3f800000,0xbf800000,0x3f800000,0xbf800000,0x3f80,0xbf80,0x3f80,0xbf80,
0x3f800000,0xbf800000,0x3f800000,0xbf800000,0x3f80,0xbf80,0x3f80,0xbf80,0x3f800000,0xbf800000,0x3f800000,0xbf800000,
0x3f7b0000,0xbf55bec4,0x3f0e3f35,0xbe48bf6d,0xbe483f80,0x3f0ebf6d,0xbf553f35,0x3f7bbec4,0xbe483f80,0x3f0ebf6d,0xbf553f35,0x3f7bbec4,
0xbf7b0000,0x3f553ec4,0xbf0ebf35,0x3e483f6d,0xbf7b0000,0x3f553ec4,0xbf0ebf35,0x3e483f6d,0x3e48bf80,0xbf0e3f6d,0x3f55bf35,0xbf7b3ec4,
0x3e48bf80,0xbf0e3f6d,0x3f55bf35,0xbf7b3ec4,0x3f7b0000,0xbf55bec4,0x3f0e3f35,0xbe48bf6d,0x3ec4bf80,0xbf6d3f35,0x3f6d0000,0xbec4bf35,
0xbf6d0000,0x3ec43f35,0x3ec4bf80,0xbf6d3f35,0xbec43f80,0x3f6dbf35,0xbf6d0000,0x3ec43f35,0x3f6d0000,0xbec4bf35,0xbec43f80,0x3f6dbf35,
0x3ec4bf80,0xbf6d3f35,0x3f6d0000,0xbec4bf35,0xbf6d0000,0x3ec43f35,0x3ec4bf80,0xbf6d3f35,0xbec43f80,0x3f6dbf35,0xbf6d0000,0x3ec43f35,
0x3f6d0000,0xbec4bf35,0xbec43f80,0x3f6dbf35,0x3f0ebf80,0xbf7b3ec4,0x3e483f35,0x3f55bf6d,0x3f550000,0x3e48bf6d,0xbf7b3f35,0x3f0e3ec4,
0x3f550000,0x3e48bf6d,0xbf7b3f35,0x3f0e3ec4,0xbf0e3f80,0x3f7bbec4,0xbe48bf35,0xbf553f6d,0xbf0e3f80,0x3f7bbec4,0xbe48bf35,0xbf553f6d,
0xbf550000,0xbe483f6d,0x3f7bbf35,0xbf0ebec4,0xbf550000,0xbe483f6d,0x3f7bbf35,0xbf0ebec4,0x3f0ebf80,0xbf7b3ec4,0x3e483f35,0x3f55bf6d,
0xbf353f80,0x3f350000,0x3f35bf80,0xbf350000,0x3f350000,0x3f35bf80,0xbf350000,0xbf353f80,0xbf353f80,0x3f350000,0x3f35bf80,0xbf350000,
0x3f350000,0x3f35bf80,0xbf350000,0xbf353f80,0xbf353f80,0x3f350000,0x3f35bf80,0xbf350000,0x3f350000,0x3f35bf80,0xbf350000,0xbf353f80,
0xbf353f80,0x3f350000,0x3f35bf80,0xbf350000,0x3f350000,0x3f35bf80,0xbf350000,0xbf353f80,0xbf0e0000,0xbf7b3f6d,0xbe483f35,0x3f55bec4,
0x3f55bf80,0xbe48bec4,0xbf7b3f35,0xbf0e3f6d,0x3f55bf80,0xbe48bec4,0xbf7b3f35,0xbf0e3f6d,0x3f0e0000,0x3f7bbf6d,0x3e48bf35,0xbf553ec4,
0x3f0e0000,0x3f7bbf6d,0x3e48bf35,0xbf553ec4,0xbf553f80,0x3e483ec4,0x3f7bbf35,0x3f0ebf6d,0xbf553f80,0x3e483ec4,0x3f7bbf35,0x3f0ebf6d,
0xbf0e0000,0xbf7b3f6d,0xbe483f35,0x3f55bec4,0x3f6dbf80,0x3ec4bf35,0xbec40000,0xbf6d3f35,0xbec40000,0xbf6d3f35,0xbf6d3f80,0xbec43f35,
0xbf6d3f80,0xbec43f35,0x3ec40000,0x3f6dbf35,0x3ec40000,0x3f6dbf35,0x3f6dbf80,0x3ec4bf35,0x3f6dbf80,0x3ec4bf35,0xbec40000,0xbf6d3f35,
0xbec40000,0xbf6d3f35,0xbf6d3f80,0xbec43f35,0xbf6d3f80,0xbec43f35,0x3ec40000,0x3f6dbf35,0x3ec40000,0x3f6dbf35,0x3f6dbf80,0x3ec4bf35,
0xbf7b3f80,0xbf553f6d,0xbf0e3f35,0xbe483ec4,0xbe480000,0xbf0e3ec4,0xbf553f35,0xbf7b3f6d,0xbe480000,0xbf0e3ec4,0xbf553f35,0xbf7b3f6d,
0x3f7bbf80,0x3f55bf6d,0x3f0ebf35,0x3e48bec4,0x3f7bbf80,0x3f55bf6d,0x3f0ebf35,0x3e48bec4,0x3e480000,0x3f0ebec4,0x3f55bf35,0x3f7bbf6d,
0x3e480000,0x3f0ebec4,0x3f55bf35,0x3f7bbf6d,0xbf7b3f80,0xbf553f6d,0xbf0e3f35,0xbe483ec4,0xbf808000,0x3f808000,0xbf808000,0x3f808000,
0x3f80,0xbf80,0x3f80,0xbf80,0xbf808000,0x3f808000,0xbf808000,0x3f808000,0x3f80,0xbf80,0x3f80,0xbf80,
0xbf808000,0x3f808000,0xbf808000,0x3f808000,0x3f80,0xbf80,0x3f80,0xbf80,0xbf808000,0x3f808000,0xbf808000,0x3f808000,
0x3f80,0xbf80,0x3f80,0xbf80,0xbe483f80,0x3f0ebf6d,0xbf553f35,0x3f7bbec4,0xbf7b8000,0x3f553ec4,0xbf0ebf35,0x3e483f6d,
0xbf7b0000,0x3f553ec4,0xbf0ebf35,0x3e483f6d,0x3e48bf80,0xbf0e3f6d,0x3f55bf35,0xbf7b3ec4,0x3e48bf80,0xbf0e3f6d,0x3f55bf35,0xbf7b3ec4,
0x3f7b8000,0xbf55bec4,0x3f0e3f35,0xbe48bf6d,0x3f7b0000,0xbf55bec4,0x3f0e3f35,0xbe48bf6d,0xbe483f80,0x3f0ebf6d,0xbf553f35,0x3f7bbec4,
0x3f6d8000,0xbec4bf35,0xbec43f80,0x3f6dbf35,0x3ec4bf80,0xbf6d3f35,0x3f6d0000,0xbec4bf35,0xbf6d8000,0x3ec43f35,0x3ec4bf80,0xbf6d3f35,
0xbec43f80,0x3f6dbf35,0xbf6d0000,0x3ec43f35,0x3f6d8000,0xbec4bf35,0xbec43f80,0x3f6dbf35,0x3ec4bf80,0xbf6d3f35,0x3f6d0000,0xbec4bf35,
0xbf6d8000,0x3ec43f35,0x3ec4bf80,0xbf6d3f35,0xbec43f80,0x3f6dbf35,0xbf6d0000,0x3ec43f35,0x3f550000,0x3e48bf6d,0xbf7b3f35,0x3f0e3ec4,
0xbf0e3f80,0x3f7bbec4,0xbe48bf35,0xbf553f6d,0xbf0e3f80,0x3f7bbec4,0xbe48bf35,0xbf553f6d,0xbf558000,0xbe483f6d,0x3f7bbf35,0xbf0ebec4,
0xbf550000,0xbe483f6d,0x3f7bbf35,0xbf0ebec4,0x3f0ebf80,0xbf7b3ec4,0x3e483f35,0x3f55bf6d,0x3f0ebf80,0xbf7b3ec4,0x3e483f35,0x3f55bf6d,
0x3f558000,0x3e48bf6d,0xbf7b3f35,0x3f0e3ec4,0xbf358000,0xbf353f80,0x3f358000,0x3f35bf80,0xbf353f80,0x3f350000,0x3f35bf80,0xbf350000,
0xbf358000,0xbf353f80,0x3f358000,0x3f35bf80,0xbf353f80,0x3f350000,0x3f35bf80,0xbf350000,0xbf358000,0xbf353f80,0x3f358000,0x3f35bf80,
0xbf353f80,0x3f350000,0x3f35bf80,0xbf350000,0xbf358000,0xbf353f80,0x3f358000,0x3f35bf80,0xbf353f80,0x3f350000,0x3f35bf80,0xbf350000,
0x3f55bf80,0xbe48bec4,0xbf7b3f35,0xbf0e3f6d,0x3f0e8000,0x3f7bbf6d,0x3e48bf35,0xbf553ec4,0x3f0e0000,0x3f7bbf6d,0x3e48bf35,0xbf553ec4,
0xbf553f80,0x3e483ec4,0x3f7bbf35,0x3f0ebf6d,0xbf553f80,0x3e483ec4,0x3f7bbf35,0x3f0ebf6d,0xbf0e8000,0xbf7b3f6d,0xbe483f35,0x3f55bec4,
0xbf0e0000,0xbf7b3f6d,0xbe483f35,0x3f55bec4,0x3f55bf80,0xbe48bec4,0xbf7b3f35,0xbf0e3f6d,0x3ec48000,0x3f6dbf35,0x3f6dbf80,0x3ec4bf35,
0x3f6dbf80,0x3ec4bf35,0xbec40000,0xbf6d3f35,0xbec48000,0xbf6d3f35,0xbf6d3f80,0xbec43f35,0xbf6d3f80,0xbec43f35,0x3ec40000,0x3f6dbf35,
0x3ec48000,0x3f6dbf35,0x3f6dbf80,0x3ec4bf35,0x3f6dbf80,0x3ec4bf35,0xbec40000,0xbf6d3f35,0xbec48000,0xbf6d3f35,0xbf6d3f80,0xbec43f35,
0xbf6d3f80,0xbec43f35,0x3ec40000,0x3f6dbf35,0xbe480000,0xbf0e3ec4,0xbf553f35,0xbf7b3f6d,0x3f7bbf80,0x3f55bf6d,0x3f0ebf35,0x3e48bec4,
0x3f7bbf80,0x3f55bf6d,0x3f0ebf35,0x3e48bec4,0x3e488000,0x3f0ebec4,0x3f55bf35,0x3f7bbf6d,0x3e480000,0x3f0ebec4,0x3f55bf35,0x3f7bbf6d,
0xbf7b3f80,0xbf553f6d,0xbf0e3f35,0xbe483ec4,0xbf7b3f80,0xbf553f6d,0xbf0e3f35,0xbe483ec4,0xbe488000,0xbf0e3ec4,0xbf553f35,0xbf7b3f6d,
0xbf803f80,0xbf803f80,0xbf803f80,0xbf803f80,0x0,0x0,0x0,0x0,0xbf803f80,0xbf803f80,0xbf803f80,0xbf803f80,
0x0,0x0,0x0,0x0,0xbf803f80,0xbf803f80,0xbf803f80,0xbf803f80,0x0,0x0,0x0,0x0,
0xbf803f80,0xbf803f80,0xbf803f80,0xbf803f80,0x0,0x0,0x0,0x0,0xbe480000,0xbf0e3ec4,0xbf553f35,0xbf7b3f6d,
0xbf7b3f80,0xbf553f6d,0xbf0e3f35,0xbe483ec4,0xbf7b3f80,0xbf553f6d,0xbf0e3f35,0xbe483ec4,0x3e480000,0x3f0ebec4,0x3f55bf35,0x3f7bbf6d,
0x3e480000,0x3f0ebec4,0x3f55bf35,0x3f7bbf6d,0x3f7bbf80,0x3f55bf6d,0x3f0ebf35,0x3e48bec4,0x3f7bbf80,0x3f55bf6d,0x3f0ebf35,0x3e48bec4,
0xbe480000,0xbf0e3ec4,0xbf553f35,0xbf7b3f6d,0x3f6dbf80,0x3ec4bf35,0xbec40000,0xbf6d3f35,0x3ec40000,0x3f6dbf35,0x3f6dbf80,0x3ec4bf35,
0xbf6d3f80,0xbec43f35,0x3ec40000,0x3f6dbf35,0xbec40000,0xbf6d3f35,0xbf6d3f80,0xbec43f35,0x3f6dbf80,0x3ec4bf35,0xbec40000,0xbf6d3f35,
0x3ec40000,0x3f6dbf35,0x3f6dbf80,0x3ec4bf35,0xbf6d3f80,0xbec43f35,0x3ec40000,0x3f6dbf35,0xbec40000,0xbf6d3f35,0xbf6d3f80,0xbec43f35,
0x3f55bf80,0xbe48bec4,0xbf7b3f35,0xbf0e3f6d,0xbf0e0000,0xbf7b3f6d,0xbe483f35,0x3f55bec4,0xbf0e0000,0xbf7b3f6d,0xbe483f35,0x3f55bec4,
0xbf553f80,0x3e483ec4,0x3f7bbf35,0x3f0ebf6d,0xbf553f80,0x3e483ec4,0x3f7bbf35,0x3f0ebf6d,0x3f0e0000,0x3f7bbf6d,0x3e48bf35,0xbf553ec4,
0x3f0e0000,0x3f7bbf6d,0x3e48bf35,0xbf553ec4,0x3f55bf80,0xbe48bec4,0xbf7b3f35,0xbf0e3f6d,0xbf353f80,0x3f350000,0x3f35bf80,0xbf350000,
0xbf350000,0xbf353f80,0x3f350000,0x3f35bf80,0xbf353f80,0x3f350000,0x3f35bf80,0xbf350000,0xbf350000,0xbf353f80,0x3f350000,0x3f35bf80,
0xbf353f80,0x3f350000,0x3f35bf80,0xbf350000,0xbf350000,0xbf353f80,0x3f350000,0x3f35bf80,0xbf353f80,0x3f350000,0x3f35bf80,0xbf350000,
0xbf350000,0xbf353f80,0x3f350000,0x3f35bf80,0x3f550000,0x3e48bf6d,0xbf7b3f35,0x3f0e3ec4,0x3f0ebf80,0xbf7b3ec4,0x3e483f35,0x3f55bf6d,
0x3f0ebf80,0xbf7b3ec4,0x3e483f35,0x3f55bf6d,0xbf550000,0xbe483f6d,0x3f7bbf35,0xbf0ebec4,0xbf550000,0xbe483f6d,0x3f7bbf35,0xbf0ebec4,
0xbf0e3f80,0x3f7bbec4,0xbe48bf35,0xbf553f6d,0xbf0e3f80,0x3f7bbec4,0xbe48bf35,0xbf553f6d,0x3f550000,0x3e48bf6d,0xbf7b3f35,0x3f0e3ec4,
0x3ec4bf80,0xbf6d3f35,0x3f6d0000,0xbec4bf35,0x3f6d0000,0xbec4bf35,0xbec43f80,0x3f6dbf35,0xbec43f80,0x3f6dbf35,0xbf6d0000,0x3ec43f35,
0xbf6d0000,0x3ec43f35,0x3ec4bf80,0xbf6d3f35,0x3ec4bf80,0xbf6d3f35,0x3f6d0000,0xbec4bf35,0x3f6d0000,0xbec4bf35,0xbec43f80,0x3f6dbf35,
0xbec43f80,0x3f6dbf35,0xbf6d0000,0x3ec43f35,0xbf6d0000,0x3ec43f35,0x3ec4bf80,0xbf6d3f35,0xbe483f80,0x3f0ebf6d,0xbf553f35,0x3f7bbec4,
0x3f7b0000,0xbf55bec4,0x3f0e3f35,0xbe48bf6d,0x3f7b0000,0xbf55bec4,0x3f0e3f35,0xbe48bf6d,0x3e48bf80,0xbf0e3f6d,0x3f55bf35,0xbf7b3ec4,
0x3e48bf80,0xbf0e3f6d,0x3f55bf35,0xbf7b3ec4,0xbf7b0000,0x3f553ec4,0xbf0ebf35,0x3e483f6d,0xbf7b0000,0x3f553ec4,0xbf0ebf35,0x3e483f6d,
0xbe483f80,0x3f0ebf6d,0xbf553f35,0x3f7bbec4,0x80008000,0x80008000,0x80008000,0x80008000,0xbf803f80,0xbf803f80,0xbf803f80,0xbf803f80,
0x80008000,0x80008000,0x80008000,0x80008000,0xbf803f80,0xbf803f80,0xbf803f80,0xbf803f80,0x80008000,0x80008000,0x80008000,0x80008000,
0xbf803f80,0xbf803f80,0xbf803f80,0xbf803f80,0x80008000,0x80008000,0x80008000,0x80008000,0xbf803f80,0xbf803f80,0xbf803f80,0xbf803f80,
0xbf7b3f80,0xbf553f6d,0xbf0e3f35,0xbe483ec4,0x3e488000,0x3f0ebec4,0x3f55bf35,0x3f7bbf6d,0x3e480000,0x3f0ebec4,0x3f55bf35,0x3f7bbf6d,
0x3f7bbf80,0x3f55bf6d,0x3f0ebf35,0x3e48bec4,0x3f7bbf80,0x3f55bf6d,0x3f0ebf35,0x3e48bec4,0xbe488000,0xbf0e3ec4,0xbf553f35,0xbf7b3f6d,
0xbe480000,0xbf0e3ec4,0xbf553f35,0xbf7b3f6d,0xbf7b3f80,0xbf553f6d,0xbf0e3f35,0xbe483ec4,0xbec48000,0xbf6d3f35,0xbf6d3f80,0xbec43f35,
0x3f6dbf80,0x3ec4bf35,0xbec40000,0xbf6d3f35,0x3ec48000,0x3f6dbf35,0x3f6dbf80,0x3ec4bf35,0xbf6d3f80,0xbec43f35,0x3ec40000,0x3f6dbf35,
0xbec48000,0xbf6d3f35,0xbf6d3f80,0xbec43f35,0x3f6dbf80,0x3ec4bf35,0xbec40000,0xbf6d3f35,0x3ec48000,0x3f6dbf35,0x3f6dbf80,0x3ec4bf35,
0xbf6d3f80,0xbec43f35,0x3ec40000,0x3f6dbf35,0xbf0e0000,0xbf7b3f6d,0xbe483f35,0x3f55bec4,0xbf553f80,0x3e483ec4,0x3f7bbf35,0x3f0ebf6d,
0xbf553f80,0x3e483ec4,0x3f7bbf35,0x3f0ebf6d,0x3f0e8000,0x3f7bbf6d,0x3e48bf35,0xbf553ec4,0x3f0e0000,0x3f7bbf6d,0x3e48bf35,0xbf553ec4,
0x3f55bf80,0xbe48bec4,0xbf7b3f35,0xbf0e3f6d,0x3f55bf80,0xbe48bec4,0xbf7b3f35,0xbf0e3f6d,0xbf0e8000,0xbf7b3f6d,0xbe483f35,0x3f55bec4,
0x3f358000,0x3f35bf80,0xbf358000,0xbf353f80,0xbf353f80,0x3f350000,0x3f35bf80,0xbf350000,0x3f358000,0x3f35bf80,0xbf358000,0xbf353f80,
0xbf353f80,0x3f350000,0x3f35bf80,0xbf350000,0x3f358000,0x3f35bf80,0xbf358000,0xbf353f80,0xbf353f80,0x3f350000,0x3f35bf80,0xbf350000,
0x3f358000,0x3f35bf80,0xbf358000,0xbf353f80,0xbf353f80,0x3f350000,0x3f35bf80,0xbf350000,0x3f0ebf80,0xbf7b3ec4,0x3e483f35,0x3f55bf6d,
0xbf558000,0xbe483f6d,0x3f7bbf35,0xbf0ebec4,0xbf550000,0xbe483f6d,0x3f7bbf35,0xbf0ebec4,0xbf0e3f80,0x3f7bbec4,0xbe48bf35,0xbf553f6d,
0xbf0e3f80,0x3f7bbec4,0xbe48bf35,0xbf553f6d,0x3f558000,0x3e48bf6d,0xbf7b3f35,0x3f0e3ec4,0x3f550000,0x3e48bf6d,0xbf7b3f35,0x3f0e3ec4,
0x3f0ebf80,0xbf7b3ec4,0x3e483f35,0x3f55bf6d,0xbf6d8000,0x3ec43f35,0x3ec4bf80,0xbf6d3f35,0x3ec4bf80,0xbf6d3f35,0x3f6d0000,0xbec4bf35,
0x3f6d8000,0xbec4bf35,0xbec43f80,0x3f6dbf35,0xbec43f80,0x3f6dbf35,0xbf6d0000,0x3ec43f35,0xbf6d8000,0x3ec43f35,0x3ec4bf80,0xbf6d3f35,
0x3ec4bf80,0xbf6d3f35,0x3f6d0000,0xbec4bf35,0x3f6d8000,0xbec4bf35,0xbec43f80,0x3f6dbf35,0xbec43f80,0x3f6dbf35,0xbf6d0000,0x3ec43f35,
0x3f7b0000,0xbf55bec4,0x3f0e3f35,0xbe48bf6d,0x3e48bf80,0xbf0e3f6d,0x3f55bf35,0xbf7b3ec4,0x3e48bf80,0xbf0e3f6d,0x3f55bf35,0xbf7b3ec4,
0xbf7b8000,0x3f553ec4,0xbf0ebf35,0x3e483f6d,0xbf7b0000,0x3f553ec4,0xbf0ebf35,0x3e483f6d,0xbe483f80,0x3f0ebf6d,0xbf553f35,0x3f7bbec4,
0xbe483f80,0x3f0ebf6d,0xbf553f35,0x3f7bbec4,0x3f7b8000,0xbf55bec4,0x3f0e3f35,0xbe48bf6d,0x3f80,0xbf80,0x3f80,0xbf80,
0xbf800000,0x3f800000,0xbf800000,0x3f800000,0x3f80,0xbf80,0x3f80,0xbf80,0xbf800000,0x3f800000,0xbf800000,0x3f800000,
0x3f80,0xbf80,0x3f80,0xbf80,0xbf800000,0x3f800000,0xbf800000,0x3f800000,0x3f80,0xbf80,0x3f80,0xbf80,
0xbf800000,0x3f800000,0xbf800000,0x3f800000,0xbf7b0000,0x3f55bec4,0xbf0e3f35,0x3e48bf6d,0x3e483f80,0xbf0ebf6d,0x3f553f35,0xbf7bbec4,
0x3e483f80,0xbf0ebf6d,0x3f553f35,0xbf7bbec4,0x3f7b0000,0xbf553ec4,0x3f0ebf35,0xbe483f6d,0x3f7b0000,0xbf553ec4,0x3f0ebf35,0xbe483f6d,
0xbe48bf80,0x3f0e3f6d,0xbf55bf35,0x3f7b3ec4,0xbe48bf80,0x3f0e3f6d,0xbf55bf35,0x3f7b3ec4,0xbf7b0000,0x3f55bec4,0xbf0e3f35,0x3e48bf6d,
0xbec4bf80,0x3f6d3f35,0xbf6d0000,0x3ec4bf35,0x3f6d0000,0xbec43f35,0xbec4bf80,0x3f6d3f35,0x3ec43f80,0xbf6dbf35,0x3f6d0000,0xbec43f35,
0xbf6d0000,0x3ec4bf35,0x3ec43f80,0xbf6dbf35,0xbec4bf80,0x3f6d3f35,0xbf6d0000,0x3ec4bf35,0x3f6d0000,0xbec43f35,0xbec4bf80,0x3f6d3f35,
0x3ec43f80,0xbf6dbf35,0x3f6d0000,0xbec43f35,0xbf6d0000,0x3ec4bf35,0x3ec43f80,0xbf6dbf35,0xbf0ebf80,0x3f7b3ec4,0xbe483f35,0xbf55bf6d,
0xbf550000,0xbe48bf6d,0x3f7b3f35,0xbf0e3ec4,0xbf550000,0xbe48bf6d,0x3f7b3f35,0xbf0e3ec4,0x3f0e3f80,0xbf7bbec4,0x3e48bf35,0x3f553f6d,
0x3f0e3f80,0xbf7bbec4,0x3e48bf35,0x3f553f6d,0x3f550000,0x3e483f6d,0xbf7bbf35,0x3f0ebec4,0x3f550000,0x3e483f6d,0xbf7bbf35,0x3f0ebec4,
0xbf0ebf80,0x3f7b3ec4,0xbe483f35,0xbf55bf6d,0x3f353f80,0xbf350000,0xbf35bf80,0x3f350000,0xbf350000,0xbf35bf80,0x3f350000,0x3f353f80,
0x3f353f80,0xbf350000,0xbf35bf80,0x3f350000,0xbf350000,0xbf35bf80,0x3f350000,0x3f353f80,0x3f353f80,0xbf350000,0xbf35bf80,0x3f350000,
0xbf350000,0xbf35bf80,0x3f350000,0x3f353f80,0x3f353f80,0xbf350000,0xbf35bf80,0x3f350000,0xbf350000,0xbf35bf80,0x3f350000,0x3f353f80,
0x3f0e0000,0x3f7b3f6d,0x3e483f35,0xbf55bec4,0xbf55bf80,0x3e48bec4,0x3f7b3f35,0x3f0e3f6d,0xbf55bf80,0x3e48bec4,0x3f7b3f35,0x3f0e3f6d,
0xbf0e0000,0xbf7bbf6d,0xbe48bf35,0x3f553ec4,0xbf0e0000,0xbf7bbf6d,0xbe48bf35,0x3f553ec4,0x3f553f80,0xbe483ec4,0xbf7bbf35,0xbf0ebf6d,
0x3f553f80,0xbe483ec4,0xbf7bbf35,0xbf0ebf6d,0x3f0e0000,0x3f7b3f6d,0x3e483f35,0xbf55bec4,0xbf6dbf80,0xbec4bf35,0x3ec40000,0x3f6d3f35,
0x3ec40000,0x3f6d3f35,0x3f6d3f80,0x3ec43f35,0x3f6d3f80,0x3ec43f35,0xbec40000,0xbf6dbf35,0xbec40000,0xbf6dbf35,0xbf6dbf80,0xbec4bf35,
0xbf6dbf80,0xbec4bf35,0x3ec40000,0x3f6d3f35,0x3ec40000,0x3f6d3f35,0x3f6d3f80,0x3ec43f35,0x3f6d3f80,0x3ec43f35,0xbec40000,0xbf6dbf35,
0xbec40000,0xbf6dbf35,0xbf6dbf80,0xbec4bf35,0x3f7b3f80,0x3f553f6d,0x3f0e3f35,0x3e483ec4,0x3e480000,0x3f0e3ec4,0x3f553f35,0x3f7b3f6d,
0x3e480000,0x3f0e3ec4,0x3f553f35,0x3f7b3f6d,0xbf7bbf80,0xbf55bf6d,0xbf0ebf35,0xbe48bec4,0xbf7bbf80,0xbf55bf6d,0xbf0ebf35,0xbe48bec4,
0xbe480000,0xbf0ebec4,0xbf55bf35,0xbf7bbf6d,0xbe480000,0xbf0ebec4,0xbf55bf35,0xbf7bbf6d,0x3f7b3f80,0x3f553f6d,0x3f0e3f35,0x3e483ec4,
0x3f808000,0xbf808000,0x3f808000,0xbf808000,0x3f80,0xbf80,0x3f80,0xbf80,0x3f808000,0xbf808000,0x3f808000,0xbf808000,
0x3f80,0xbf80,0x3f80,0xbf80,0x3f808000,0xbf808000,0x3f808000,0xbf808000,0x3f80,0xbf80,0x3f80,0xbf80,
0x3f808000,0xbf808000,0x3f808000,0xbf808000,0x3f80,0xbf80,0x3f80,0xbf80,0x3e483f80,0xbf0ebf6d,0x3f553f35,0xbf7bbec4,
0x3f7b8000,0xbf553ec4,0x3f0ebf35,0xbe483f6d,0x3f7b0000,0xbf553ec4,0x3f0ebf35,0xbe483f6d,0xbe48bf80,0x3f0e3f6d,0xbf55bf35,0x3f7b3ec4,
0xbe48bf80,0x3f0e3f6d,0xbf55bf35,0x3f7b3ec4,0xbf7b8000,0x3f55bec4,0xbf0e3f35,0x3e48bf6d,0xbf7b0000,0x3f55bec4,0xbf0e3f35,0x3e48bf6d,
0x3e483f80,0xbf0ebf6d,0x3f553f35,0xbf7bbec4,0xbf6d8000,0x3ec4bf35,0x3ec43f80,0xbf6dbf35,0xbec4bf80,0x3f6d3f35,0xbf6d0000,0x3ec4bf35,
0x3f6d8000,0xbec43f35,0xbec4bf80,0x3f6d3f35,0x3ec43f80,0xbf6dbf35,0x3f6d0000,0xbec43f35,0xbf6d8000,0x3ec4bf35,0x3ec43f80,0xbf6dbf35,
0xbec4bf80,0x3f6d3f35,0xbf6d0000,0x3ec4bf35,0x3f6d8000,0xbec43f35,0xbec4bf80,0x3f6d3f35,0x3ec43f80,0xbf6dbf35,0x3f6d0000,0xbec43f35,
0xbf550000,0xbe48bf6d,0x3f7b3f35,0xbf0e3ec4,0x3f0e3f80,0xbf7bbec4,0x3e48bf35,0x3f553f6d,0x3f0e3f80,0xbf7bbec4,0x3e48bf35,0x3f553f6d,
0x3f558000,0x3e483f6d,0xbf7bbf35,0x3f0ebec4,0x3f550000,0x3e483f6d,0xbf7bbf35,0x3f0ebec4,0xbf0ebf80,0x3f7b3ec4,0xbe483f35,0xbf55bf6d,
0xbf0ebf80,0x3f7b3ec4,0xbe483f35,0xbf55bf6d,0xbf558000,0xbe48bf6d,0x3f7b3f35,0xbf0e3ec4,0x3f358000,0x3f353f80,0xbf358000,0xbf35bf80,
0x3f353f80,0xbf350000,0xbf35bf80,0x3f350000,0x3f358000,0x3f353f80,0xbf358000,0xbf35bf80,0x3f353f80,0xbf350000,0xbf35bf80,0x3f350000,
0x3f358000,0x3f353f80,0xbf358000,0xbf35bf80,0x3f353f80,0xbf350000,0xbf35bf80,0x3f350000,0x3f358000,0x3f353f80,0xbf358000,0xbf35bf80,
0x3f353f80,0xbf350000,0xbf35bf80,0x3f350000,0xbf55bf80,0x3e48bec4,0x3f7b3f35,0x3f0e3f6d,0xbf0e8000,0xbf7bbf6d,0xbe48bf35,0x3f553ec4,
0xbf0e0000,0xbf7bbf6d,0xbe48bf35,0x3f553ec4,0x3f553f80,0xbe483ec4,0xbf7bbf35,0xbf0ebf6d,0x3f553f80,0xbe483ec4,0xbf7bbf35,0xbf0ebf6d,
0x3f0e8000,0x3f7b3f6d,0x3e483f35,0xbf55bec4,0x3f0e0000,0x3f7b3f6d,0x3e483f35,0xbf55bec4,0xbf55bf80,0x3e48bec4,0x3f7b3f35,0x3f0e3f6d,
0xbec48000,0xbf6dbf35,0xbf6dbf80,0xbec4bf35,0xbf6dbf80,0xbec4bf35,0x3ec40000,0x3f6d3f35,0x3ec48000,0x3f6d3f35,0x3f6d3f80,0x3ec43f35,
0x3f6d3f80,0x3ec43f35,0xbec40000,0xbf6dbf35,0xbec48000,0xbf6dbf35,0xbf6dbf80,0xbec4bf35,0xbf6dbf80,0xbec4bf35,0x3ec40000,0x3f6d3f35,
0x3ec48000,0x3f6d3f35,0x3f6d3f80,0x3ec43f35,0x3f6d3f80,0x3ec43f35,0xbec40000,0xbf6dbf35,0x3e480000,0x3f0e3ec4,0x3f553f35,0x3f7b3f6d,
0xbf7bbf80,0xbf55bf6d,0xbf0ebf35,0xbe48bec4,0xbf7bbf80,0xbf55bf6d,0xbf0ebf35,0xbe48bec4,0xbe488000,0xbf0ebec4,0xbf55bf35,0xbf7bbf6d,
0xbe480000,0xbf0ebec4,0xbf55bf35,0xbf7bbf6d,0x3f7b3f80,0x3f553f6d,0x3f0e3f35,0x3e483ec4,0x3f7b3f80,0x3f553f6d,0x3f0e3f35,0x3e483ec4,
0x3e488000,0x3f0e3ec4,0x3f553f35,0x3f7b3f6d,
};
__device__ __align__(1024) uint8_t g_hT[32 * 262144];
__device__ __align__(1024) bf16 g_U[128 * 2 * 8 * 1024];
__device__ __align__(128) float g_gp[128 * 256];
__device__ __align__(128) uint4 g_agg[16 * 512];
#define CS 32
#define NREP 1
#define NREPH 4
constexpr int RS = 9 * CS;
__device__ __align__(128) unsigned g_cnt[32 * RS];
constexpr int CNT_U = 0, CNT_V = 1, CNT_DONE = 2, CNT_EPOCH = 3, CNT_H = 4  ;
#define PROFK(i) do { } while (0)
#define PROFC(i) do { } while (0)
#define PROF(i) do { } while (0)
#define PROFX(i) do { } while (0)
#define PROFR(i) do { } while (0)
#define PROFT(i) do { } while (0)
#define PROFS(i) do { } while (0)
#define PROFG(i) do { } while (0)

constexpr int SLOT = 32768;
constexpr int OFF_HS = 4 * SLOT;
constexpr int OFF_W = OFF_HS + 16384;
constexpr int OFF_F = OFF_W + 2 * 18432;
constexpr int OFF_G = OFF_F + 8192;
constexpr int OFF_K = OFF_G + 1024;
constexpr int OFF_GW = OFF_K + 2048;
constexpr int OFF_U = 6 * SLOT;
constexpr int OFF_BAR = OFF_U + 32768;
constexpr int OFF_SC = OFF_BAR + 384;
constexpr int OFF_KEPT = OFF_SC + 1024;
constexpr int OFF_PROF = OFF_KEPT + 64;
constexpr int SMEM_BYTES = OFF_PROF;
constexpr int BAR_FULL = 0  , BAR_U = 11, BAR_W = 12  , BAR_F = 14  ,
              BAR_EMPTY = 17  , BAR_HW = 22  , BAR_WR = 25, BAR_VW = 26, BAR_S1 = 27,
              BAR_XC = 28  , BAR_HR = 32,
              BAR_C = 34  , BAR_HD = 36  ;

#define DEVI __device__ __forceinline__
constexpr unsigned SPIN_LIMIT = 1u << 22;

DEVI uint32_t smem_u32(const void* p) { return (uint32_t)__cvta_generic_to_shared(p); }
DEVI uint64_t gtime() { uint64_t t; asm volatile("mov.u64 %0, %%globaltimer;" : "=l"(t)); return t; }
DEVI void mbar_init(uint32_t bar, uint32_t cnt) { asm volatile("mbarrier.init.shared::cta.b64 [%0], %1;" :: "r"(bar), "r"(cnt) : "memory"); }
DEVI void mbar_expect_tx(uint32_t bar, uint32_t bytes) { asm volatile("mbarrier.arrive.expect_tx.shared::cta.b64 _, [%0], %1;" :: "r"(bar), "r"(bytes) : "memory"); }
DEVI void mbar_arrive(uint32_t bar) { asm volatile("mbarrier.arrive.shared::cta.b64 _, [%0];" :: "r"(bar) : "memory"); }
#define WAIT_LOOP "{\n.reg .pred p;\n.reg .u32 n;\nmov.u32 n, 0;\n" \
                  "LW:\nmbarrier.try_wait.parity.shared::cta.b64 p, [%0], %1;\n@p bra LD;\n" \
                  "add.u32 n, n, 1;\nsetp.lt.u32 p, n, 131072;\n@p bra LW;\nLD:\n"
DEVI void mbar_wait(uint32_t bar, uint32_t parity) { asm volatile(WAIT_LOOP "}" :: "r"(bar), "r"(parity) : "memory"); }
DEVI void warp_arrive(uint32_t bar) { asm volatile("{\n.reg .pred p;\nelect.sync _|p, 0xffffffff;\n@p mbarrier.arrive.shared::cta.b64 _, [%0];\n}" :: "r"(bar) : "memory"); }
DEVI bool elect() {
    uint32_t p;
    asm volatile("{\n.reg .pred P;\nelect.sync _|P, 0xffffffff;\nselp.u32 %0, 1, 0, P;\n}" : "=r"(p));
    return p;
}
DEVI void fence_barrier_init() { asm volatile("fence.mbarrier_init.release.cluster;" ::: "memory"); }
DEVI void fence_proxy_async_smem() { asm volatile("fence.proxy.async.shared::cta;" ::: "memory"); }
#define HF 1
#define FPOS 0
DEVI void helper_sync() { asm volatile("bar.sync 1, 128;" ::: "memory"); }

DEVI void pause(unsigned n) {
    asm volatile("{\n.reg .pred p;\n.reg .u32 a, b;\nmov.u32 a, %%clock;\n"
                 "LP:\nmov.u32 b, %%clock;\nsub.u32 b, b, a;\nsetp.lt.u32 p, b, %0;\n@p bra LP;\n}" :: "r"(n) : "memory");
}
DEVI void sched_fence() { asm volatile("{\n.reg .pred p;\n.reg .b32 n;\nLP:\nactivemask.b32 n;\nsetp.eq.u32 p, n, 0;\n@p bra LP;\n}" ::: "memory"); }
#define P_POLL 0
#define NPOLL 1
DEVI void wait_counter(const unsigned* p, unsigned target) {
    unsigned v[NPOLL];
    auto ld = [&](int i) { asm volatile("ld.relaxed.gpu.global.u32 %0, [%1];" : "=r"(v[i]) : "l"(p) : "memory"); };
#pragma unroll
    for (int i = 0; i < NPOLL; i++) { if (i) pause(200); ld(i); }
#pragma unroll 1
    for (unsigned n = 0; n < SPIN_LIMIT; n++) {
#pragma unroll
        for (int i = 0; i < NPOLL; i++) {
            if ((int)(v[i] - target) >= 0) return;
            if (P_POLL) pause(P_POLL);
            ld(i);
        }
    }
}
DEVI void signal_counter(unsigned* p) {
#pragma unroll
    for (int r = 0; r < NREP; r++) asm volatile("red.relaxed.gpu.global.add.u32 [%0], 1;" :: "l"(p + r * RS) : "memory");
}

DEVI void tma_load_3d(uint32_t dst, const CUtensorMap* map, uint32_t bar, int c0, int c1, int c2) {
    asm volatile("cp.async.bulk.tensor.3d.shared::cluster.global.mbarrier::complete_tx::bytes [%0], [%1, {%3, %4, %5}], [%2];"
        :: "r"(dst), "l"(map), "r"(bar), "r"(c0), "r"(c1), "r"(c2) : "memory");
}
DEVI void tma_load_4d(uint32_t dst, const CUtensorMap* map, uint32_t bar, int c0, int c1, int c2, int c3) {
    asm volatile("cp.async.bulk.tensor.4d.shared::cluster.global.mbarrier::complete_tx::bytes [%0], [%1, {%3, %4, %5, %6}], [%2];"
        :: "r"(dst), "l"(map), "r"(bar), "r"(c0), "r"(c1), "r"(c2), "r"(c3) : "memory");
}
DEVI void tma_load_5d(uint32_t dst, const CUtensorMap* map, uint32_t bar, int c0, int c3, int c4) {
    asm volatile("cp.async.bulk.tensor.5d.shared::cluster.global.mbarrier::complete_tx::bytes [%0], [%1, {%3, %6, %6, %4, %5}], [%2];"
        :: "r"(dst), "l"(map), "r"(bar), "r"(c0), "r"(c3), "r"(c4), "r"(0) : "memory");
}
DEVI void tma_store_4d(const CUtensorMap* map, uint32_t src, int c0, int c1, int c2, int c3) {
    asm volatile("cp.async.bulk.tensor.4d.global.shared::cta.bulk_group [%0, {%2, %3, %4, %5}], [%1];"
        :: "l"(map), "r"(src), "r"(c0), "r"(c1), "r"(c2), "r"(c3) : "memory");
}
DEVI void bulk_load(uint32_t dst, const void* src, uint32_t bytes, uint32_t bar) {
    asm volatile("cp.async.bulk.shared::cluster.global.mbarrier::complete_tx::bytes [%0], [%1], %2, [%3];"
        :: "r"(dst), "l"(src), "r"(bytes), "r"(bar) : "memory");
}
DEVI void bulk_prefetch_l2(const void* src, uint32_t bytes) {
    asm volatile("cp.async.bulk.prefetch.L2.global [%0], %1;" :: "l"(src), "r"(bytes) : "memory");
}
DEVI void tma_store_3d(const CUtensorMap* map, uint32_t src, int c0, int c1, int c2) {
    asm volatile("cp.async.bulk.tensor.3d.global.shared::cta.bulk_group [%0, {%2, %3, %4}], [%1];"
        :: "l"(map), "r"(src), "r"(c0), "r"(c1), "r"(c2) : "memory");
}
DEVI void bulk_store(void* dst, uint32_t src, uint32_t bytes) {
    asm volatile("cp.async.bulk.global.shared::cta.bulk_group [%0], [%1], %2;" :: "l"(dst), "r"(src), "r"(bytes) : "memory");
}
DEVI void bulk_commit() { asm volatile("cp.async.bulk.commit_group;" ::: "memory"); }
DEVI void bulk_wait0() { asm volatile("cp.async.bulk.wait_group 0;" ::: "memory"); }

DEVI void wgmma_fence() { asm volatile("wgmma.fence.sync.aligned;" ::: "memory"); }
DEVI void wgmma_commit() { asm volatile("wgmma.commit_group.sync.aligned;" ::: "memory"); }
template<int N> DEVI void wgmma_wait() { asm volatile("wgmma.wait_group.sync.aligned %0;" :: "n"(N) : "memory"); }
template<int N> DEVI void wgmma_wait_all(float (&d)[N]) {
    wgmma_wait<0>();
#pragma unroll
    for (int i = 0; i < N; i++) asm volatile("" : "+f"(d[i]) :: "memory");
}
template<int R> DEVI void reg_alloc() { asm volatile("setmaxnreg.inc.sync.aligned.u32 %0;" :: "n"(R)); }
template<int R> DEVI void reg_dealloc() { asm volatile("setmaxnreg.dec.sync.aligned.u32 %0;" :: "n"(R)); }

constexpr uint32_t SB0 = 1024;
DEVI uint64_t make_desc(uint32_t off, uint32_t lbo, uint32_t sbo, uint32_t mode = 1) {
    return (uint64_t)(((SB0 + off) >> 4) | ((lbo >> 4) << 16)) | ((uint64_t)((sbo >> 4) | (mode << 30)) << 32);
}

#define ACC8(a, o) "+f"(a[o+0]), "+f"(a[o+1]), "+f"(a[o+2]), "+f"(a[o+3]), "+f"(a[o+4]), "+f"(a[o+5]), "+f"(a[o+6]), "+f"(a[o+7])
#define OUT8(a, o) "=f"(a[o+0]), "=f"(a[o+1]), "=f"(a[o+2]), "=f"(a[o+3]), "=f"(a[o+4]), "=f"(a[o+5]), "=f"(a[o+6]), "=f"(a[o+7])
#define ACC32(a, o) ACC8(a, o), ACC8(a, o+8), ACC8(a, o+16), ACC8(a, o+24)

#define SS_N128 "{\n.reg .pred p;\nsetp.ne.b32 p, %66, 0;\n" \
        "wgmma.mma_async.sync.aligned.m64n128k16.f32.bf16.bf16 " \
        "{%0, %1, %2, %3, %4, %5, %6, %7, %8, %9, %10, %11, %12, %13, %14, %15, " \
        "%16, %17, %18, %19, %20, %21, %22, %23, %24, %25, %26, %27, %28, %29, %30, %31, " \
        "%32, %33, %34, %35, %36, %37, %38, %39, %40, %41, %42, %43, %44, %45, %46, %47, " \
        "%48, %49, %50, %51, %52, %53, %54, %55, %56, %57, %58, %59, %60, %61, %62, %63}, " \
        "%64, %65, p, 1, 1, %67, %68;\n}\n"
template<int TA, int TB>
DEVI void wgmma_n128(float (&d)[64], uint64_t da, uint64_t db, int scale_d) {
    asm volatile(SS_N128 : ACC32(d, 0), ACC32(d, 32) : "l"(da), "l"(db), "r"(scale_d), "n"(TA), "n"(TB));
}
DEVI void wgmma_n128_set(float (&d)[64], uint64_t da, uint64_t db) {
    asm volatile(SS_N128 : OUT8(d, 0), OUT8(d, 8), OUT8(d, 16), OUT8(d, 24), OUT8(d, 32), OUT8(d, 40), OUT8(d, 48), OUT8(d, 56) : "l"(da), "l"(db), "n"(0), "n"(0), "n"(1));
}
#define SS_N16 "{\n.reg .pred p;\nsetp.ne.b32 p, 0, 0;\n" \
        "wgmma.mma_async.sync.aligned.m64n16k16.f32.bf16.bf16 " \
        "{%0, %1, %2, %3, %4, %5, %6, %7}, %8, %9, p, 1, 1, %10, 0;\n}\n"
template<int TA> DEVI void wgmma_n16(float* d, uint64_t da, uint64_t db) {
    asm volatile(SS_N16 : OUT8(d, 0) : "l"(da), "l"(db), "n"(TA));
}
#define SS_N8 "{\n.reg .pred p;\nsetp.ne.b32 p, %6, 0;\n" \
        "wgmma.mma_async.sync.aligned.m64n8k16.f32.bf16.bf16 {%0, %1, %2, %3}, %4, %5, p, 1, 1, 0, 0;\n}\n"
DEVI void wgmma_n8(float (&d)[4], uint64_t da, uint64_t db, bool add) {
    if (add) asm volatile(SS_N8 : "+f"(d[0]), "+f"(d[1]), "+f"(d[2]), "+f"(d[3]) : "l"(da), "l"(db), "n"(1));
    else asm volatile(SS_N8 : "=f"(d[0]), "=f"(d[1]), "=f"(d[2]), "=f"(d[3]) : "l"(da), "l"(db), "n"(0));
}
#define RS_N64 "{\n.reg .pred p;\nsetp.ne.b32 p, %37, 0;\n" \
        "wgmma.mma_async.sync.aligned.m64n64k16.f32.bf16.bf16 " \
        "{%0, %1, %2, %3, %4, %5, %6, %7, %8, %9, %10, %11, %12, %13, %14, %15, " \
        "%16, %17, %18, %19, %20, %21, %22, %23, %24, %25, %26, %27, %28, %29, %30, %31}, " \
        "{%32, %33, %34, %35}, %36, p, 1, 1, %38;\n}\n"
template<int SCALE_D, int TB = 0>
DEVI void wgmma_rs_n64(float (&d)[32], const uint32_t (&a)[4], uint64_t db) {
    if (SCALE_D) asm volatile(RS_N64 : ACC32(d, 0) : "r"(a[0]), "r"(a[1]), "r"(a[2]), "r"(a[3]), "l"(db), "n"(1), "n"(TB));
    else asm volatile(RS_N64 : OUT8(d, 0), OUT8(d, 8), OUT8(d, 16), OUT8(d, 24) : "r"(a[0]), "r"(a[1]), "r"(a[2]), "r"(a[3]), "l"(db), "n"(0), "n"(TB));
}
#define SS_N64 "{\n.reg .pred p;\nsetp.ne.b32 p, %34, 0;\n" \
        "wgmma.mma_async.sync.aligned.m64n64k16.f32.bf16.bf16 " \
        "{%0, %1, %2, %3, %4, %5, %6, %7, %8, %9, %10, %11, %12, %13, %14, %15, " \
        "%16, %17, %18, %19, %20, %21, %22, %23, %24, %25, %26, %27, %28, %29, %30, %31}, " \
        "%32, %33, p, 1, 1, 0, 1;\n}\n"
template<int SCALE_D> DEVI void wgmma_ss_n64(float (&d)[32], uint64_t da, uint64_t db) {
    if (SCALE_D) asm volatile(SS_N64 : ACC32(d, 0) : "l"(da), "l"(db), "n"(1));
    else asm volatile(SS_N64 : OUT8(d, 0), OUT8(d, 8), OUT8(d, 16), OUT8(d, 24) : "l"(da), "l"(db), "n"(0));
}
DEVI void ldsm_x4_t(uint32_t (&r)[4], uint32_t addr) {
    asm volatile("ldmatrix.sync.aligned.m8n8.x4.trans.shared.b16 {%0, %1, %2, %3}, [%4];"
        : "=r"(r[0]), "=r"(r[1]), "=r"(r[2]), "=r"(r[3]) : "r"(addr) : "memory");
}
DEVI void ldsm_x4(uint32_t (&r)[4], uint32_t addr) {
    asm volatile("ldmatrix.sync.aligned.m8n8.x4.shared.b16 {%0, %1, %2, %3}, [%4];"
        : "=r"(r[0]), "=r"(r[1]), "=r"(r[2]), "=r"(r[3]) : "r"(addr) : "memory");
}
DEVI void stsm_x4(uint32_t addr, uint32_t r0, uint32_t r1, uint32_t r2, uint32_t r3) {
    asm volatile("stmatrix.sync.aligned.m8n8.x4.shared.b16 [%0], {%1, %2, %3, %4};"
        :: "r"(addr), "r"(r0), "r"(r1), "r"(r2), "r"(r3) : "memory");
}
DEVI void stsm_x4_t(uint32_t addr, uint32_t r0, uint32_t r1, uint32_t r2, uint32_t r3) {
    asm volatile("stmatrix.sync.aligned.m8n8.x4.trans.shared.b16 [%0], {%1, %2, %3, %4};"
        :: "r"(addr), "r"(r0), "r"(r1), "r"(r2), "r"(r3) : "memory");
}
DEVI uint32_t movm(uint32_t a) { uint32_t d; asm volatile("movmatrix.sync.aligned.m8n8.trans.b16 %0, %1;" : "=r"(d) : "r"(a)); return d; }
DEVI uint32_t pack2(float lo, float hi) { uint32_t d; asm("cvt.rn.bf16x2.f32 %0, %1, %2;" : "=r"(d) : "f"(hi), "f"(lo)); return d; }
DEVI float bf_lo(uint32_t v) { return __uint_as_float(v << 16); }
DEVI float bf_hi(uint32_t v) { return __uint_as_float(v & 0xffff0000u); }
DEVI float bf_round(float v) { return __bfloat162float(__float2bfloat16_rn(v)); }
DEVI uint32_t bf_mul2(uint32_t a, uint32_t b) { uint32_t d; asm("mul.rn.bf16x2 %0, %1, %2;" : "=r"(d) : "r"(a), "r"(b)); return d; }
DEVI uint32_t bf_add2(uint32_t a, uint32_t b) { uint32_t d; asm("add.rn.bf16x2 %0, %1, %2;" : "=r"(d) : "r"(a), "r"(b)); return d; }
DEVI uint32_t bf_sub2(uint32_t a, uint32_t b) { uint32_t d; asm("sub.rn.bf16x2 %0, %1, %2;" : "=r"(d) : "r"(a), "r"(b)); return d; }
DEVI uint4 lds128u(uint32_t a) { uint4 v; asm volatile("ld.shared.v4.u32 {%0, %1, %2, %3}, [%4];" : "=r"(v.x), "=r"(v.y), "=r"(v.z), "=r"(v.w) : "r"(a) : "memory"); return v; }
DEVI void sts128u(uint32_t a, uint32_t x, uint32_t y, uint32_t z, uint32_t w) { asm volatile("st.shared.v4.u32 [%0], {%1, %2, %3, %4};" :: "r"(a), "r"(x), "r"(y), "r"(z), "r"(w) : "memory"); }
DEVI uint2 lds64u(uint32_t a) { uint2 v; asm volatile("ld.shared.v2.u32 {%0, %1}, [%2];" : "=r"(v.x), "=r"(v.y) : "r"(a) : "memory"); return v; }
DEVI uint32_t ldg32u(const void* p) { uint32_t v; asm volatile("ld.global.nc.u32 %0, [%1];" : "=r"(v) : "l"(p) : "memory"); return v; }
DEVI void sts64(uint32_t a, float x, float y) { asm volatile("st.shared.v2.f32 [%0], {%1, %2};" :: "r"(a), "f"(x), "f"(y) : "memory"); }
DEVI void sts32(uint32_t a, uint32_t v) { asm volatile("st.shared.u32 [%0], %1;" :: "r"(a), "r"(v) : "memory"); }
DEVI uint32_t lds16(uint32_t a) { uint32_t v; asm volatile("ld.shared.u16 %0, [%1];" : "=r"(v) : "r"(a) : "memory"); return v; }
DEVI void cmul2(uint32_t& x, uint32_t& y, uint32_t c, uint32_t s, uint32_t n) {
    asm("{\n.reg .b32 t, u;\nmul.rn.bf16x2 t, %1, %4;\nmul.rn.bf16x2 u, %1, %2;\n"
        "fma.rn.bf16x2 %1, %0, %3, u;\nfma.rn.bf16x2 %0, %0, %2, t;\n}" : "+r"(x), "+r"(y) : "r"(c), "r"(s), "r"(n));
}
DEVI uint32_t neg2(uint32_t s) { uint32_t n; asm volatile("xor.b32 %0, %1, 0x80008000;" : "=r"(n) : "r"(s)); return n; }
DEVI void cmul2(uint32_t& x, uint32_t& y, uint32_t c, uint32_t s) { cmul2(x, y, c, s, neg2(s)); }
DEVI void cmul2c(uint32_t& x, uint32_t& y, uint32_t c, uint32_t s) { cmul2(x, y, c, neg2(s), s); }
DEVI void sts16(uint32_t a, float v) { asm volatile("st.shared.u16 [%0], %1;" :: "r"(a), "r"(pack2(v, v)) : "memory"); }

DEVI float2 cmul(float2 a, float2 b) { return make_float2(fmaf(a.x, b.x, -a.y * b.y), fmaf(a.x, b.y, a.y * b.x)); }
DEVI float2 cfma(float2 a, float2 b, float2 c) { return make_float2(fmaf(a.x, b.x, fmaf(-a.y, b.y, c.x)), fmaf(a.x, b.y, fmaf(a.y, b.x, c.y))); }

DEVI float2 csq(float2 a) {
    float y;
    asm("{\n.reg .f32 t;\nmul.ftz.f32 t, %1, %2;\nmul.ftz.f32 %0, t, 0f40000000;\n}" : "=f"(y) : "f"(a.x), "f"(a.y));
    return make_float2(fmaf(a.x, a.x, -a.y * a.y), y);
}

struct Params {
    const bf16 *lam_re, *lam_im, *log_dt, *dskip, *gate_w, *c_re, *c_im, *b_re, *b_im, *x;
    int swapB;
    int2 tile[130];
};

#define P_W0 0
#define P_W1 0
#define P_R8F 0
#define P_R8I 0
#define P_CF 0
#define P_S1 0
#define P_SK 0
#define R8_POLL 8
#define R8B 1
#define SCB 32
#define C0 1
#define R8A 4
DEVI void radix8(uint32_t sb, bool inv, int w, int lane, int bar) {
    const uint64_t dg = make_desc(OFF_G + (inv ? 512 : 0), 128, 256, 0), da = make_desc(OFF_U, 16, 16384);
    float acc[2][64];
    wgmma_fence();
#pragma unroll
    for (int j = 0; j < 8; j++) wgmma_n16<1>(acc[0] + 8 * j, da + 64 * j, dg);
    wgmma_commit();
    sched_fence();
    asm volatile("" : "+r"(lane));
    const int kk = lane & 7, ch = 2 * w + ((lane >> 3) & 1);
    const uint32_t st = sb + OFF_U + (inv ? (lane >> 4) * 16384 + kk * 128 + ((ch ^ kk) << 4)
        : (kk & 1) * 16384 + (kk >> 2) * 2048 + (lane >> 4) * 1024 + (w >> 1) * 128 + ((((kk & 2) * 2 + ((ch & 3) ^ (kk >> 2) ^ (2 * (kk & 1)))) ^ (w >> 1)) << 4));
    uint32_t sa[4];
#pragma unroll
    for (int i = 0; i < 4; i++) { sa[i] = inv ? (st ^ (i << 4)) + i * 1024 : (st ^ (i << 5)) + i * 256; asm volatile("" : "+r"(sa[i])); }
    const int warp = inv;
    sched_fence();
    if (R8A) {
        wgmma_fence();
#pragma unroll
        for (int j = 0; j < R8A; j++) wgmma_n16<1>(acc[1] + 8 * j, da + 64 * (8 + j), dg);
        wgmma_commit();
    }
    PROFC(8);
#pragma unroll
    for (int i = 0; i < 2; i++) {
        if (i || !R8A) wgmma_wait<0>(); else wgmma_wait<1>();
#pragma unroll
        for (int j = 0; j < 64; j++) asm volatile("" : "+f"(acc[i][j]) :: "memory");
        PROFC(9 + 2 * i);
        asm volatile("bar.sync %0, 128;" :: "r"(bar) : "memory");
        if (!i && R8A < 8) wgmma_fence();
#pragma unroll
        for (int j = 0; j < 8; j++) {
            const float* a = acc[i] + 8 * j;
            if (!i && j + R8A < 8) wgmma_n16<1>(acc[1] + 8 * (j + R8A), da + 64 * (8 + j + R8A), dg);
            stsm_x4_t(sa[j & 3] + (2 * i + (j >> 2)) * 4096, pack2(a[0], a[1]), pack2(a[2], a[3]), pack2(a[4], a[5]), pack2(a[6], a[7]));
            if ((P_R8F || P_R8I) && (j & 1) && j < 7 && (i || j + R8A >= 7)) pause(inv ? P_R8I : P_R8F);
        }
        if (!i && R8A < 8) wgmma_commit();
        PROFC(10 + 2 * i);
        if (i ? inv || !(FPOS & 1) : inv && HF) fence_proxy_async_smem();
        __syncwarp();
        if (inv) warp_arrive(sb + OFF_BAR + 8 * BAR_VW);
    }
}

template<int N> DEVI void c_take(float (&acc)[32], uint32_t (&p)[16]) {
    wgmma_wait<N>();
#pragma unroll
    for (int i = 0; i < 32; i++) asm volatile("" : "+f"(acc[i]) :: "memory");
#pragma unroll
    for (int i = 0; i < 16; i++) p[i] = pack2(acc[2 * i], acc[2 * i + 1]);
}
DEVI uint64_t desc_at(uint64_t d, uint32_t o) { return (d & 0xffffffff00000000ull) | ((uint32_t)d + o); }
DEVI void c_cols(float (&acc)[32], uint64_t df, uint64_t db, int o) {
    wgmma_fence();
    wgmma_ss_n64<0>(acc, df, desc_at(db, o));
#pragma unroll
    for (int s = 1; s < 4; s++) wgmma_ss_n64<1>(acc, df + 2 * s, desc_at(db, o + 256 * s));
    wgmma_commit();
}

DEVI void phase_c(uint32_t sb, int ps, bool rot, int w, int lane) {
    const int warp = ps, bar = 5 + ps;
    PROFC(0);
    const uint32_t rb = sb + OFF_U + ps * 16384;
    const uint64_t df = make_desc(OFF_F, 16, 1024), db = make_desc(OFF_U + ps * 16384, 16, 1024);
    float acc[2][32];
    c_cols(acc[0], df, db, 0);
    c_cols(acc[1], df, db, 128);
    sched_fence();
    asm volatile("" : "+r"(lane));
    const int g = lane & 7, l3 = (lane >> 3) & 1, l4 = lane >> 4;
    uint32_t wf[2][4][4];
    const uint32_t wo = sb + OFF_W + (1 - ps) * 18432 + l4 * 9216 + g * 64 + ((w ^ (g >> 1)) << 4);
    uint32_t wd = wo + l3 * 1152, wm[2] = {wo + 4608 + (((rot ? 4 : 3) - l3) & 3) * 1152, wo + 4608 + ((rot ? 2 : 1) - l3) * 1152};
    uint32_t xa = rb + w * 4096 + l4 * 1024 + g * 128 + (((4 * l3) ^ g) << 4);
    uint32_t oa = rb + (4 * w + (g >> 1)) * 1024 + (1 - l3) * 512 + (((4 * (g & 1) + l4) ^ (4 - 4 * l3) ^ (g >> 1)) << 4);
    auto load_w = [&](int h) {
#pragma unroll
        for (int j = 0; j < 4; j++) ldsm_x4_t(wf[h][j], (j < 2 ? wd + h * 2304 : wm[h]) + (j & 1) * 512);
    };
    uint32_t tw[8][3];
    {
        const float a0 = (float)(8 * w + (lane >> 2)) * 0.0061359231515425649f, q2 = (float)(2 * (lane & 3)), p16 = (float)(16 * ps);
        const float b0 = a0 * (q2 + p16), b1 = a0 * (q2 - p16);
#pragma unroll
        for (int j = 0; j < 4; j++) {
            const float u = fmaf(a0, 8.f * j, j < 2 ? b0 : b1), v = u + a0, su = __sinf(u), sv = __sinf(v);
            tw[j][0] = pack2(__cosf(u), __cosf(v)); tw[j][1] = pack2(-su, -sv); tw[j][2] = pack2(su, sv);
        }
    }
#pragma unroll
    for (int j = 0; j < 4; j++) asm volatile("" : "+r"(tw[j][0]), "+r"(tw[j][1]), "+r"(tw[j][2]));
    asm volatile("" : "+r"(wd), "+r"(wm[0]), "+r"(wm[1]), "+r"(xa), "+r"(oa));
    sched_fence();
    auto twiddle = [&](uint32_t& x, uint32_t& y, int j) { cmul2(x, y, tw[j][0], tw[j][1], tw[j][2]); };
#pragma unroll
    for (int h = 0; h < 2; h++) {
        uint32_t p[16], a[4][4];
        c_take<1>(acc[h], p);
        if (h == 0) PROFC(1);
#pragma unroll
        for (int i = 0; i < 8; i++) {
            twiddle(p[2 * i], p[2 * i + 1], (i & 3) ^ h);
            a[(i & 3) ^ h][i >> 2] = p[2 * i];
            a[(i & 3) ^ h][2 + (i >> 2)] = p[2 * i + 1];
        }
        wgmma_fence();
        wgmma_rs_n64<0>(acc[h], a[0], desc_at(df, 4 * ps));
        wgmma_rs_n64<1>(acc[h], a[1], desc_at(df, 4 * ps + 2));
        wgmma_rs_n64<1>(acc[h], a[2], desc_at(df, 4 - 4 * ps));
        wgmma_rs_n64<1>(acc[h], a[3], desc_at(df, 6 - 4 * ps));
        wgmma_commit();
        load_w(h);
    }
    PROFC(2);
#pragma unroll
    for (int h = 0; h < 2; h++) {
        uint32_t p[16], a[4][4];
        c_take<1>(acc[h], p);
#pragma unroll
        for (int i = 0; i < 8; i++) {
            const int j = i >> 1, r = i & 1;
            if (j < 2) cmul2(p[4 * j + r], p[4 * j + 2 + r], wf[h][j][r], wf[h][j][2 + r]);
            else cmul2c(p[4 * j + r], p[4 * j + 2 + r], wf[h][j][r], wf[h][j][2 + r]);
            a[j][r] = p[4 * j + 2 + r];
            a[j][2 + r] = p[4 * j + r];
        }
        wgmma_fence();
        wgmma_rs_n64<0>(acc[h], a[0], df);
#pragma unroll
        for (int j = 1; j < 4; j++) wgmma_rs_n64<1>(acc[h], a[j], df + 2 * j);
        wgmma_commit();
    }
    PROFC(3);
#pragma unroll
    for (int j = 0; j < 12; j++) tw[4 + j / 3][j % 3] = ps ? tw[(j / 3) ^ 2][j % 3] : tw[j / 3][j % 3];
    uint32_t p[16];
    auto put = [&](int h) {
#pragma unroll
        for (int i = 0; i < 8; i++) twiddle(p[4 * (i >> 1) + (i & 1)], p[4 * (i >> 1) + 2 + (i & 1)], 4 + (i >> 1));
        if (!h) {
#pragma unroll
            for (int i = 0; i < 16; i++) asm volatile("" : "+r"(p[i]) :: "memory");
            asm volatile("bar.sync %0, 128;" :: "r"(bar) : "memory");
        }
#pragma unroll
        for (int j = 0; j < 4; j++) stsm_x4((xa ^ (j << 4)) + h * 2048, p[4 * j], p[4 * j + 1], p[4 * j + 2], p[4 * j + 3]);
        if (h && ps && !(FPOS & 2)) fence_proxy_async_smem();
    };
    c_take<1>(acc[0], p);
    put(0);
    c_take<0>(acc[1], p);
    if (!ps) put(1);
    else {
        float fin[2][64];
        auto cols = [&](int n) {
            wgmma_fence();
            wgmma_n128_set(fin[n], df, make_desc(OFF_U + n * 16384, 2048, 1024));
#pragma unroll
            for (int s = 1; s < 4; s++) wgmma_n128<0, 1>(fin[n], df + 2 * s, make_desc(OFF_U + n * 16384, 2048, 1024) + 256 * s, 1);
            wgmma_commit();
            sched_fence();
        };
        cols(0);
#pragma unroll
        for (int i = 0; i < 16; i++) asm volatile("" : "+r"(p[i]) :: "memory");
        put(1);
        PROFC(4);
#pragma unroll
        for (int n = 0; n < 2; n++) {
            wgmma_wait_all(fin[n]);
            asm volatile("bar.sync 6, 128;" ::: "memory");
            if (!n && (FPOS & 2)) fence_proxy_async_smem();
            if (!n) cols(1);
#pragma unroll
            for (int i = 0; i < 8; i++) {
                const int r = i >> 1;
                const float* a = fin[n] + 8 * i;
                stsm_x4((oa ^ ((r ^ (2 * (i & 1))) << 4)) + r * 128 + (n - 1) * 16384, pack2(a[0], a[1]), pack2(a[2], a[3]), pack2(a[4], a[5]), pack2(a[6], a[7]));
                if (P_CF && (i & 1) && i < 7) pause(P_CF);
            }
        }
        if (!(FPOS & 4)) fence_proxy_async_smem();
        asm volatile("bar.sync 6, 128;" ::: "memory");
        if (FPOS & 4) fence_proxy_async_smem();
    }
    PROFC(5);
}

#define P_T 80
#define P_C 300
#define PACE_HA 100
#define PACE_HB 0
#define HN 4
#define PACE_V 100
#define VFIRST 4
#define K0 2
#define P_K 0
#define NB0 2
#define VK 63
#define LEAD 1
#define K_XE 58
#define PACE_H 200
#define T_W0 2000
#define T_XS 1600
#define D_XS 0
#define P_XS 500
#define T_G 0
#define T_BA 400
#define T_W1 3000
#define P_W 0
#define P_XE 600
#define P_R0 0
#define P_CAR 300
#define HWZ 2
#define R_REL 1
#define R_MID 4
#define W_EARLY 0
#define SEP 0
#define UN 1
#define FA0 16
#define P_CARB 200
#define D_CAR 20
#define HPOLL 1
#define P_HP 0
#define PF0 0
#define NPF 1
#define PFM 63
#define PFT 0
#define T_PFT 0
#define N_T 1
#define HS0 3
#define T_B2 4000
#define T_W 4500
#define PACE_U 200
#define PACE_L 0
#define T_FA 0
#define REG_M 216
#define REG_H 72
#define NS 4
#define QM1 42
#define QM2 36
#define SLOT_OF(k) (((k) + 1) % 4)
DEVI void tma_prefetch_4d(const CUtensorMap* map, int c0, int c1, int c2, int c3) {
    asm volatile("cp.async.bulk.prefetch.tensor.4d.L2.global [%0, {%1, %2, %3, %4}];" :: "l"(map), "r"(c0), "r"(c1), "r"(c2), "r"(c3) : "memory");
}
DEVI void bar_sync(int id, int n) { asm volatile("bar.sync %0, %1;" :: "r"(id), "r"(n) : "memory"); }
DEVI void bar_arrive(int id, int n) { asm volatile("bar.arrive %0, %1;" :: "r"(id), "r"(n) : "memory"); }
DEVI uint4 ldg128(const void* p) { uint4 v; asm volatile("ld.global.nc.v4.u32 {%0, %1, %2, %3}, [%4];" : "=r"(v.x), "=r"(v.y), "=r"(v.z), "=r"(v.w) : "l"(p)); return v; }
DEVI uint32_t ldg16(const void* p) { uint32_t v; asm volatile("ld.global.nc.u16 %0, [%1];" : "=r"(v) : "l"(p)); return v; }
DEVI uint32_t bf_fma2(uint32_t a, uint32_t b, uint32_t c) { uint32_t d; asm("fma.rn.bf16x2 %0, %1, %2, %3;" : "=r"(d) : "r"(a), "r"(b), "r"(c)); return d; }
DEVI uint32_t lo2(uint32_t a) { uint32_t d; asm("{\n.reg .b16 l, h;\nmov.b32 {l, h}, %1;\nmov.b32 %0, {l, l};\n}" : "=r"(d) : "r"(a)); return d; }
DEVI uint32_t hi2(uint32_t a) { uint32_t d; asm("{\n.reg .b16 l, h;\nmov.b32 {l, h}, %1;\nmov.b32 %0, {h, h};\n}" : "=r"(d) : "r"(a)); return d; }
DEVI void bulk_wait_read() { asm volatile("cp.async.bulk.wait_group.read 0;" ::: "memory"); }

DEVI float lds32f(uint32_t a) { float v; asm volatile("ld.shared.f32 %0, [%1];" : "=f"(v) : "r"(a) : "memory"); return v; }
DEVI uint32_t mbar_test(uint32_t bar, uint32_t parity) {
    uint32_t ok;
    asm volatile("{\n.reg .pred p;\nmbarrier.test_wait.parity.shared::cta.b64 p, [%1], %2;\nselp.u32 %0, 1, 0, p;\n}" : "=r"(ok) : "r"(bar), "r"(parity) : "memory");
    return ok;
}
template<int TA> DEVI void ring_steps(float (&acc)[2][64], uint32_t sb, uint32_t fb, int n, int ns, int s, uint32_t ph, int first_bar, int last_bar, int pi) {
    const uint64_t da0 = TA ? make_desc(0, 2048, 256, 3) : make_desc(0, 16, 1024), db0 = make_desc(16384, 16, 1024);
    const uint32_t fe = fb + 8 * ns, de = sb + OFF_BAR + 8 * BAR_EMPTY - fb;
    uint32_t eb = sb + OFF_BAR + 8 * BAR_HR, f = fb + 8 * s;
    uint64_t da = da0 + (uint32_t)(s * 2048), db = db0 + (uint32_t)(s * 2048);
    bool first = true;
    if (TA) PROFT(72); else if (threadIdx.x == 0) PROFX(93);
    mbar_wait(f, ph);
    if (TA) PROFT(73);
    if (first_bar) bar_sync(first_bar, 256);
    if (TA) PROFT(74);
#pragma unroll 1
    for (;;) {
        PROFK(pi++);
        wgmma_fence();
        constexpr int QM = TA ? QM2 : QM1;
#pragma unroll
        for (int j = 0; j < 8; j++) {
            wgmma_n128<TA, 0>(acc[j & 1], da + 512 * (j & 1) + (TA ? 32 : 2) * (j >> 1), db + 2 * (j >> 1), j > 1 || !first);
            if ((QM >> j) & 1) {
                wgmma_commit();
                wgmma_wait<1>();
                if (!(QM & ((1 << j) - 1))) warp_arrive(eb);
                wgmma_fence();
            }
        }
        wgmma_commit();
        first = false;
        --n;
        if (TA && n == 0) break;
        eb = f + de;
        f += 8; da += 2048; db += 2048;
        if (f == fe) { f = fb; da = da0; db = db0; ph ^= 1; }
        const uint32_t ok = mbar_test(f, ph);
        wgmma_wait<1>();
        if (!ok) mbar_wait(f, ph);
        __syncwarp();
        if (!TA && n == 1) break;
    }
    if (!TA) {
        PROFK(pi++);
        wgmma_fence();
#pragma unroll
        for (int j = 0; j < 8; j++) {
            wgmma_n128<TA, 0>(acc[j >> 2], da + 512 * (j >> 2) + 2 * (j & 3), db + 2 * (j & 3), 1);
            if (j == 3) {
                wgmma_commit();
                wgmma_wait<1>();
                warp_arrive(eb);
                wgmma_fence();
            }
        }
        wgmma_commit();
    }
    if (last_bar) bar_arrive(last_bar, 256);
}

__global__ void __cluster_dims__(2, 1, 1) __launch_bounds__(384, 1)
fused_kernel(const __grid_constant__ CUtensorMap mapB, const __grid_constant__ CUtensorMap mapX,
             const __grid_constant__ CUtensorMap mapXs, const __grid_constant__ CUtensorMap mapU0,
             const __grid_constant__ CUtensorMap mapU2, const __grid_constant__ CUtensorMap mapXe,
             const __grid_constant__ CUtensorMap mapCre, const __grid_constant__ CUtensorMap mapCim,
             const __grid_constant__ CUtensorMap mapV, const __grid_constant__ CUtensorMap mapO,
             const __grid_constant__ CUtensorMap mapWr, const __grid_constant__ CUtensorMap mapWi,
             const __grid_constant__ CUtensorMap mapH,
             const __grid_constant__ Params P) {
    extern __shared__ __align__(1024) uint8_t sm[];
    const uint32_t sb = smem_u32(sm);
    const uint32_t bars = sb + OFF_BAR;
    const int tid = threadIdx.x;
    const int2 rc = P.tile[blockIdx.x];
    auto first_loads = [&](int k0, int k1) {
#pragma unroll 1
        for (int k = k0; k < k1; k++) {
            const uint32_t full = bars + 8 * (BAR_FULL + k), st = sb + k * SLOT;
            if (P_K && k1 == 5) pause(P_K);
            if (k1 == 5) mbar_expect_tx(full, SLOT);
            tma_load_4d(st, &mapB, full, k * 64, 0, 0, rc.x);
            tma_load_4d(st + 16384, &mapX, full, k * 64, 0, 0, rc.y);
            if (k1 < 5) mbar_expect_tx(full, SLOT);
            if (k == 0) PROFX(89);
        }
    };
    if ((tid >> 5) == 8 && elect()) {
        PROF(0);
#pragma unroll
        for (int i = 0; i < NB0; i++) mbar_init(bars + 8 * i, 1);
        fence_barrier_init();
        fence_proxy_async_smem();
        PROFX(88);
        if (rc.x >= 0) first_loads(0, K0);
        if (NB0 < 5) {
#pragma unroll
            for (int i = NB0; i < 5; i++) mbar_init(bars + 8 * i, 1);
            fence_barrier_init();
            fence_proxy_async_smem();
        }
    }
    sched_fence();
    const int b = ((unsigned)rc.x >> 24) + ((rc.x & 24) << 2) + ((rc.y >> 3) & 16) + ((rc.x >> 2) & 8) + ((rc.y >> 7) & 6) + ((rc.y >> 6) & 1);
    const bool main_cta = b < 128;
    if (b == 129) return;
    const int warp = __shfl_sync(0xffffffffu, tid >> 5, 0), lane = tid & 31;
    const int rp = (b >> 1) & 3, mq = ((b >> 3) & 2) + (b & 1), dt = ((b >> 1) & 4) + (b >> 5), tc = 4 * rp + mq;
    if (warp >= 8) {
        __syncwarp();
        reg_dealloc<REG_H>();
        if (warp == 8) { bar_arrive(0, 256); bar_arrive(4, 384); }
    }
    if (warp == 8 && elect()) {
        if (main_cta) first_loads(K0, 5);
        PROF(27);
    }
    const int cls = b == 128 ? 128 : (b & 31) ? (b & 31) + 64 * (b >> 5) : (b == 64 ? 32 : b == 32 ? 64 : b);
    if (warp > 3 && warp != 8) {
        if (elect()) {
            if (warp == 11) PROFG(0);
            if ((sb & 0x3FFFF) != SB0) __trap();
#pragma unroll 1
            for (int u = warp - 4 - (warp > 8); u < 11; u += 7) {
                mbar_init(bars + 8 * (5 + u), 1);
                if (!u) mbar_arrive(bars + 8 * (BAR_FULL + 5));
                if (u == 8) sts32(sb + OFF_KEPT + 32, 0);
                mbar_init(bars + 8 * (16 + u), u ? 4 : 1);
                mbar_init(bars + 8 * (27 + u), u < 1 ? 4 : u == 6 ? 8 : (u == 7 || u == 8) ? 64 : 1);
            }
            fence_barrier_init();
            fence_proxy_async_smem();
        }
        __syncwarp();
        bar_arrive(4, 384);
    }
    __syncwarp();
    const bool real_cls = (cls & 127) == 0;
    const int t = tid & 127;
    auto load_epoch = [&]() {
        unsigned e;
        asm volatile("ld.relaxed.gpu.global.u32 %0, [g_cnt + %1];" : "=r"(e) : "n"(CNT_EPOCH * CS * 4));
        return e + 1;
    };
    const int g = lane >> 2, q = lane & 3;

    if (warp < 8) {
        reg_alloc<REG_M>();
        const int wg = warp >> 2, w = warp & 3;
        if (tid == 0) PROFX(94);
        if (tid == 224) PROFG(8);
        auto kept = [&](int i) { uint64_t v; asm volatile("ld.volatile.shared.u64 %0, [%1];" : "=l"(v) : "r"(sb + OFF_KEPT + 8 * i) : "memory"); return v; };
        const uint32_t fb = bars + 8 * (BAR_FULL + 5 * wg);
        if (wg) {
            sched_fence();
            bar_sync(0, 256);
            uint32_t fa[16][4];
            auto load_fa = [&](int i0, int i1) {
#pragma unroll
                for (int i = i0; i < i1; i++)
                    asm volatile("ld.global.nc.L1::no_allocate.v4.u32 {%0, %1, %2, %3}, [%4];" : "=r"(fa[i][0]), "=r"(fa[i][1]), "=r"(fa[i][2]), "=r"(fa[i][3]) : "l"((const uint4*)c_tab + i * 128 + t));
            };
            {
                const int pp = (dt * 64 + 8 * (t & 64) + (t & 63)) & 1023;
                const uint32_t lr_ = ldg16(P.lam_re + pp), li_ = ldg16(P.lam_im + pp), ld_ = ldg16(P.log_dt + pp);
                const unsigned epoch = load_epoch();
                if (T_FA) pause(T_FA);
                load_fa(0, FA0);
                if (t < 64 && main_cta) g_agg[rp * 2048 + (dt + (t >> 5) * 8) * 128 + lane * 4 + mq] = make_uint4(0u, 0u, 0u, 0u);
                if (t < 4) asm volatile("st.shared.u64 [%0], %1;" :: "r"(sb + OFF_KEPT + 8 * lane),
                    "l"(lane == 0 ? (P.swapB ? 0xffffffffull : 0xffffff7full) | ((uint64_t)epoch << 32) : lane == 1 ? (uint64_t)g_agg : (uint64_t)&mapB) : "memory");
                const float lr = bf_lo(lr_), li = bf_lo(li_);
                const float dl = bf_round(expf(bf_lo(ld_)));
                const float mag = expf(dl * lr);
                float sn, cs; sincospif(dl * li * 0.31830988618379067f, &sn, &cs);
                const float2 l1 = make_float2(mag * cs, mag * sn);
                const float inv = 1.f / (lr * lr + li * li);
                const float2 cf = cmul(make_float2(l1.x - 1.f, l1.y), make_float2(lr * inv, -li * inv));
                sts128u(sb + OFF_K + 16 * t, __float_as_uint(l1.x), __float_as_uint(P.swapB ? -l1.y : l1.y),
                        P.swapB ? pack2(-cf.y, cf.x) : pack2(cf.x, -cf.y), P.swapB ? pack2(-cf.x, -cf.y) : pack2(-cf.y, -cf.x));
                if (tid == 128) PROFX(92);
            }
            {
                const int kk = (t >> 3) & 7, r = t & 7;
                float sn, cs;
                sincospif((float)(((cls + 256 * kk) * r) & 2047) * (1.f / 1024.f), &sn, &cs);
                sn *= 1.f / 1024.f; cs *= 1.f / 1024.f;
                const uint32_t gf = sb + OFF_G + kk * 16 + r * 2, gi = sb + OFF_G + 512 + r * 16 + (kk & 1) * 128 + (kk & 6);
                if (t < 64) {
                    sts16(gf, cs); sts16(gf + 128, real_cls ? 0.f : sn); sts16(gf + 256, -sn); sts16(gf + 384, real_cls ? 0.f : cs);
                    sts16(gi, cs); sts16(gi + 8, -sn); sts16(gi + 256, sn); sts16(gi + 264, cs);
                }
            }
            if (main_cta) {
                load_fa(FA0, 16);
                if (t == 0) PROFX(91);
                const uint32_t ua = sb + OFF_U + (lane >> 4) * 4096 + (8 * w + (lane & 7)) * 128 + ((((lane >> 3) & 1) ^ (lane & 7)) << 4);
                float acc[4][32];
                const uint64_t db = make_desc(OFF_U, 8192, 1024);
                uint32_t x[4][8], y[4][8];
                float gp[4][4];
#pragma unroll
                for (int m = 0; m < 6; m++) {
                    if (m >= 2) {
                        const int n = m - 2;
                        if (m < 5) wgmma_wait<1>(); else wgmma_wait<0>();
#pragma unroll
                        for (int i = 0; i < 32; i++) asm volatile("" : "+f"(acc[n][i]) :: "memory");
                        asm volatile("" : "+f"(gp[n][0]), "+f"(gp[n][2]) :: "memory");
#pragma unroll
                        for (int j = 0; j < 8; j++) { x[n][j] = pack2(acc[n][4 * j], acc[n][4 * j + 1]); y[n][j] = pack2(acc[n][4 * j + 2], acc[n][4 * j + 3]); }
                    }
                    if (m < 4) {
                        mbar_wait(bars + 8 * (BAR_XC + m), 0);
                        if (t == 0 && m == 3) PROF(8);
                        wgmma_fence();
                        wgmma_rs_n64<0, 1>(acc[m], fa[4 * m], db + 512 * m);
#pragma unroll
                        for (int j = 1; j < 4; j++) wgmma_rs_n64<1, 1>(acc[m], fa[4 * m + j], db + 512 * m + 128 * j);
#pragma unroll
                        for (int j = 0; j < 4; j++) wgmma_n8(gp[m], make_desc(OFF_U, 16, 1024) + 512 * m + 2 * j, make_desc(OFF_GW, 16, 1024) + 2 * j, j);
                        wgmma_commit();
                    }
                }
                if (t < 4) {
#pragma unroll
                    for (int j = 0; j < 8; j++) {
                        const uint32_t s0 = bf_add2(x[0][j], x[2][j]), s2 = bf_add2(x[1][j], x[3][j]), ty = bf_sub2(y[1][j], y[3][j]), sy = bf_add2(y[1][j], y[3][j]);
                        const uint32_t b0 = y[0][j], b2 = y[2][j];
                        y[1][j] = bf_sub2(x[3][j], x[1][j]); x[1][j] = bf_sub2(x[0][j], x[2][j]);
                        x[0][j] = bf_add2(s0, s2); y[0][j] = bf_sub2(s0, s2);
                        x[2][j] = bf_add2(b0, ty); y[2][j] = bf_add2(sy, b2) ^ 0x80008000u;
                        x[3][j] = bf_sub2(b0, ty); y[3][j] = bf_sub2(b2, sy);
                    }
                } else {
#pragma unroll
                    for (int j = 0; j < 8; j++) {
                        const uint32_t s0x = bf_add2(x[0][j], x[2][j]), s1x = bf_sub2(x[0][j], x[2][j]), s2x = bf_add2(x[1][j], x[3][j]), tx = bf_sub2(x[1][j], x[3][j]);
                        const uint32_t s0y = bf_add2(y[0][j], y[2][j]), s1y = bf_sub2(y[0][j], y[2][j]), s2y = bf_add2(y[1][j], y[3][j]), ty = bf_sub2(y[1][j], y[3][j]);
                        x[0][j] = bf_add2(s0x, s2x); y[0][j] = bf_add2(s0y, s2y);
                        x[1][j] = bf_add2(s1x, ty); y[1][j] = bf_sub2(s1y, tx);
                        x[2][j] = bf_sub2(s0x, s2x); y[2][j] = bf_sub2(s0y, s2y);
                        x[3][j] = bf_sub2(s1x, ty); y[3][j] = bf_add2(s1y, tx);
                    }
                }
                helper_sync();
                if (q == 0) {
#pragma unroll
                    for (int i = 0; i < 2; i++)
                        sts128u(sb + OFF_GW + (16 * w + 8 * i + g) * 16, __float_as_uint(gp[0][2 * i]), __float_as_uint(gp[1][2 * i]), __float_as_uint(gp[2][2 * i]), __float_as_uint(gp[3][2 * i]));
                }
#pragma unroll
                for (int c = 0; c < 4; c++)
#pragma unroll
                    for (int j = 0; j < 8; j += 2) {
                        stsm_x4((ua ^ (j << 4)) + c * 8192, x[c][j], x[c][j + 1], y[c][j], y[c][j + 1]);
                        if (P_S1 && (j & 2)) pause(P_S1);
                    }
                if (t == 0) PROF(21);
            }
            __syncwarp();
            warp_arrive(bars + 8 * BAR_S1);
        }
        {
            float acc[2][64];
            float2 lam8[2], lam32[2], lam64[2], l32q[2], ex[2];
            float2 ag[2][4];
            asm volatile("{\n.reg .pred p;\nsetp.lt.u32 p, %0, 128;\n@p bar.sync 4, 384;\n}" :: "r"(tid) : "memory");
            if (main_cta) {
                ring_steps<0>(acc, sb, fb, 16, 5 - wg, wg * SLOT_OF(16), 0, 2 * wg, 2 + wg, 16 * wg);
                mbar_wait(bars + 8 * BAR_S1, 0);
                const uint4* ap = (const uint4*)kept(1) + (((tc - 1 - q) >> 2) * 2048 + (dt + 8 * wg) * 128 + t);
                const uint64_t k0 = kept(0);
                const uint32_t fl = (uint32_t)k0;
                uint32_t tag = ((uint32_t)(k0 >> 32) & 7) | 8;
                float2 lam1[2], la[2], lb[2], l2[2], l4[2], wq[2], w4[2];
                uint32_t m0[2], m1[2], kr[8], ki[8];
                auto weights = [&](int i) {
                    const float2 l128 = csq(lam64[i]), l256 = csq(l128), one = make_float2(1.f, 0.f);
                    w4[i] = csq(l256);
                    wq[i] = cmul(((tc - 1 - q) & 1) ? l128 : one, ((tc - 1 - q) & 2) ? l256 : one);
                    l32q[i] = cmul((q & 1) ? la[i] : one, (q & 2) ? lb[i] : one);
                    asm volatile("" : "+f"(w4[i].x), "+f"(w4[i].y), "+f"(wq[i].x), "+f"(wq[i].y), "+f"(l32q[i].x), "+f"(l32q[i].y));
                };
#pragma unroll
                for (int i = 0; i < 2; i++) {
                    const uint4 kv = lds128u(sb + OFF_K + (64 * wg + 32 * i + (t >> 2)) * 16);
                    lam1[i] = make_float2(__uint_as_float(kv.x), __uint_as_float(kv.y));
                    m0[i] = kv.z; m1[i] = kv.w;
                    l2[i] = csq(lam1[i]); l4[i] = csq(l2[i]); lam8[i] = csq(l4[i]);
                    lam32[i] = csq(csq(lam8[i])); lam64[i] = csq(lam32[i]);
                    la[i] = q >= 1 ? lam32[i] : make_float2(0.f, 0.f); lb[i] = q >= 2 ? lam64[i] : make_float2(0.f, 0.f);
                    asm volatile("" : "+f"(lam8[i].x), "+f"(lam8[i].y), "+f"(la[i].x), "+f"(la[i].y), "+f"(lb[i].x), "+f"(lb[i].y), "+f"(lam64[i].x), "+f"(lam64[i].y));
                    if (W_EARLY) weights(i);
                }
                kr[1] = pack2(l2[0].x, l2[1].x); ki[1] = pack2(l2[0].y, l2[1].y); kr[3] = pack2(l4[0].x, l4[1].x); ki[3] = pack2(l4[0].y, l4[1].y);
                asm volatile("" : "+r"(kr[1]), "+r"(ki[1]), "+r"(kr[3]), "+r"(ki[3]));
                uint32_t pub = q == 3 && tc < 15;
                const uint4* as = ap + (2045 + mq);
                asm volatile("" : "+l"(ap), "+l"(as), "+r"(tag), "+r"(pub));
                sched_fence();
                float2 v[2];
                wgmma_wait<1>();
#pragma unroll
                for (int o = 0; o < 64; o++) asm volatile("" : "+f"(acc[0][o]) :: "memory");
#pragma unroll
                for (int i = 0; i < 2; i++) {
#pragma unroll
                    for (int r = 1; r < 8; r++) {
#pragma unroll
                        for (int c = 0; c < 4; c++) {
                            const int o = 16 * c + 4 * (r >> 1) + (r & 1), u = 16 * c + 4 * ((r - 1) >> 1) + ((r - 1) & 1);
                            const float2 n = cfma(lam1[i], make_float2(acc[i][u], acc[i][u + 2]), make_float2(acc[i][o], acc[i][o + 2]));
                            acc[i][o] = n.x; acc[i][o + 2] = n.y;
                        }
                        if (!i && r == R_REL) {
#pragma unroll
                            for (int o = 0; o < 64; o++) asm volatile("" : "+f"(acc[0][o]));
                            sched_fence();
                            wgmma_wait_all(acc[1]);
                            warp_arrive(bars + 8 * (BAR_EMPTY + SLOT_OF(15)));
                            sched_fence();
                            if (tid == 0) PROF(3);
                            if (tid == 128) PROF(25);
                            if (tid == 224) PROFG(12);
                        }
                        if (i && r == R_MID) {
#pragma unroll
                            for (int o = 0; o < 64; o++) asm volatile("" : "+f"(acc[1][o]));
                            asm volatile("" : "+f"(v[0].x), "+f"(v[0].y));
                            sched_fence();
                        }
                    }
#pragma unroll
                    for (int c = 0; c < 4; c++) ag[i][c] = make_float2(acc[i][16 * c + 13], acc[i][16 * c + 15]);
                    v[i] = ag[i][0];
#pragma unroll
                    for (int c = 1; c < 4; c++) v[i] = cfma(lam8[i], v[i], ag[i][c]);
                    float2 n = make_float2(__shfl_up_sync(0xffffffffu, v[i].x, 1, 4), __shfl_up_sync(0xffffffffu, v[i].y, 1, 4));
                    v[i] = cfma(la[i], n, v[i]);
                    n = make_float2(__shfl_up_sync(0xffffffffu, v[i].x, 2, 4), __shfl_up_sync(0xffffffffu, v[i].y, 2, 4));
                    v[i] = cfma(lb[i], n, v[i]);
                }
                asm volatile("{\n.reg .b64 a, b;\n.reg .pred p;\nsetp.ne.u32 p, %5, 0;\nmov.b64 a, {%1, %2};\nmov.b64 b, {%3, %4};\n@p st.relaxed.gpu.global.v2.b64 [%0], {a, b};\n}"
                    :: "l"(as), "r"((__float_as_uint(v[0].x) & ~15u) | tag), "r"(__float_as_uint(v[0].y)),
                       "r"((__float_as_uint(v[1].x) & ~15u) | tag), "r"(__float_as_uint(v[1].y)), "r"(pub) : "memory");
                PROFS(72 + 8 * wg);
                sched_fence();
                uint4 rr[4];
                auto poll = [&]() {
#pragma unroll
                    for (int n = 0; n < 4; n++)
                        asm volatile("{\n.reg .b64 a, b;\n.reg .pred p;\nsetp.lt.s32 p, %5, %6;\ncvt.u64.u32 a, %7;\nmov.b64 b, a;\n"
                                     "@p ld.relaxed.gpu.global.v2.b64 {a, b}, [%4];\nmov.b64 {%0, %1}, a;\nmov.b64 {%2, %3}, b;\n}"
                            : "=r"(rr[n].x), "=r"(rr[n].y), "=r"(rr[n].z), "=r"(rr[n].w) : "l"(ap - 2048 * n), "r"(4 * n), "r"(tc - q), "r"(tag) : "memory");
                };
                uint32_t hp[2][32];
                auto scale = [&](int i, uint32_t& x, uint32_t& y) {
                    const uint32_t u = bf_fma2(lo2(m0[i]), x, bf_mul2(hi2(m0[i]), y));
                    y = bf_fma2(lo2(m1[i]), x, bf_mul2(hi2(m1[i]), y)); x = u;
                };
#pragma unroll
                for (int i = 0; i < 2; i++) {
                    ex[i] = make_float2(__shfl_up_sync(0xffffffffu, v[i].x, 1, 4), __shfl_up_sync(0xffffffffu, v[i].y, 1, 4));
#pragma unroll
                    for (int j = 0; j < 16; j++) {
                        const int o = 4 * (j >> 2) + 16 * (j & 1) + ((j >> 1) & 1), u = 8 * (j >> 2) + (j & 3);
                        hp[i][u] = pack2(acc[i][o], acc[i][o + 32]); hp[i][u + 4] = pack2(acc[i][o + 2], acc[i][o + 34]);
                    }
                    if (q == 0) ex[i] = make_float2(0.f, 0.f);
                }
                if (SEP) {
#pragma unroll
                    for (int j = 0; j < 64; j++) asm volatile("" : "+r"(hp[j >> 5][j & 31]));
                    sched_fence();
                }
#pragma unroll
                for (int j = 0; j < 32; j++) scale(j >> 4, hp[j >> 4][2 * (j & 12) + (j & 3)], hp[j >> 4][2 * (j & 12) + (j & 3) + 4]);
#pragma unroll
                for (int i = 0; i < 2; i++) {
#pragma unroll
                    for (int j = 0; j < 32; j++) asm volatile("" : "+r"(hp[i][j]));
                    asm volatile("" : "+f"(ex[i].x), "+f"(ex[i].y));
                }
                PROFS(73 + 8 * wg);
                mbar_wait(bars + 8 * (wg ? BAR_HD : BAR_EMPTY + 4), 0);
                if (wg) mbar_wait(bars + 8 * BAR_WR, 0);
                pause((wg ? P_CARB : P_CAR) + D_CAR * tc);
                poll();
                sched_fence();
                uint32_t hs = sb + OFF_HS + (lane >> 4) * 1024 + w * 256 + (lane & 7) * 32 + (((lane << 1) ^ (lane << 2)) & 16), hs1 = hs + 16384 + wg * 18432;
                asm volatile("" : "+r"(hs), "+r"(hs1));
                {
                    const uint32_t cj = (fl & 128) ? 0u : 0x80008000u;
                    kr[0] = pack2(lam1[0].x, lam1[1].x); ki[0] = pack2(lam1[0].y, lam1[1].y) ^ cj; kr[7] = pack2(lam8[0].x, lam8[1].x); ki[7] = pack2(lam8[0].y, lam8[1].y) ^ cj;
                    ki[1] ^= cj; ki[3] ^= cj;
                    kr[2] = kr[1]; ki[2] = ki[1]; cmul2(kr[2], ki[2], kr[0], ki[0]);
                    const uint32_t n4 = neg2(ki[3]);
#pragma unroll
                    for (int j = 0; j < 3; j++) { kr[4 + j] = kr[j]; ki[4 + j] = ki[j]; cmul2(kr[4 + j], ki[4 + j], kr[3], ki[3], n4); }
#pragma unroll
                    for (int j = 0; j < 8; j++) asm volatile("" : "+r"(kr[j]), "+r"(ki[j]));
                    if (!W_EARLY) { weights(0); weights(1); }
                }
                sched_fence();
                float2 pt[2];
                auto sum = [&]() {
                    uint32_t bad = 0;
#pragma unroll
                    for (int j = 0; j < 4; j++) bad |= (rr[j].x ^ tag) | (rr[j].z ^ tag);
#pragma unroll
                    for (int i = 0; i < 2; i++) {
                        auto val = [&](int n) { return make_float2(__uint_as_float(i ? rr[n].z : rr[n].x), __uint_as_float(i ? rr[n].w : rr[n].y)); };
                        pt[i] = cmul(wq[i], cfma(w4[i], cfma(w4[i], cfma(w4[i], val(3), val(2)), val(1)), val(0)));
                        asm volatile("" : "+f"(pt[i].x), "+f"(pt[i].y));
                    }
                    return __any_sync(0xffffffffu, bad & 15);
                };
                if (sum()) {
#pragma unroll 1
                    for (unsigned n = 0; n < SPIN_LIMIT; n++) {
                        if (n < 3) PROFS(74 + 8 * wg + n);
                        poll();
                        if (!sum()) break;
                    }
                }
#pragma unroll
                for (int i = 0; i < 2; i++) {
                    float2 part = pt[i];
                    part.x += __shfl_xor_sync(0xffffffffu, part.x, 1); part.y += __shfl_xor_sync(0xffffffffu, part.y, 1);
                    part.x += __shfl_xor_sync(0xffffffffu, part.x, 2); part.y += __shfl_xor_sync(0xffffffffu, part.y, 2);
                    ex[i] = cfma(l32q[i], part, ex[i]);
#pragma unroll
                    for (int c = 0; c < 4; c++) { const float2 e = cfma(lam8[i], ex[i], ag[i][c]); ag[i][c] = ex[i]; ex[i] = e; }
                }
                if (t == 0) PROF(4 + 25 * wg);
#pragma unroll
                for (int i = 0; i < 2; i++) {
                    uint32_t cr[2], ci[2], cn[2];
#pragma unroll
                    for (int c = 0; c < 2; c++) { cr[c] = pack2(ag[i][c].x, ag[i][c + 2].x); ci[c] = pack2(ag[i][c].y, ag[i][c + 2].y); scale(i, cr[c], ci[c]); cn[c] = ci[c] ^ 0x80008000u; }
#pragma unroll
                    for (int n = 0; n < 4; n++) {
                        uint32_t* h = &hp[i][16 * (n & 1) + 4 * (n >> 1)];
                        if (fl & (256 << (4 * i + n))) {
#pragma unroll
                            for (int j = 0; j < 8; j++) {
                                const uint32_t x = kr[4 * (n & 1) + (j >> 1)], y = ki[4 * (n & 1) + (j >> 1)];
                                uint32_t& d = h[j + (j & 4)];
                                d = bf_fma2(i ? hi2(x) : lo2(x), (n & 2) ? ci[j & 1] : cr[j & 1], bf_fma2(i ? hi2(y) : lo2(y), (n & 2) ? cr[j & 1] : cn[j & 1], d));
                            }
                        }
                        stsm_x4((i ? hs1 : hs) + n * 4096, h[0], h[1], h[2], h[3]);
                        stsm_x4((i ? hs1 : hs) + n * 4096 + 2048, h[8], h[9], h[10], h[11]);
                        if (4 * i + n == HS0 - 1 || 4 * i + n == 7) {
                            if (4 * i + n == 7 || HF) fence_proxy_async_smem();
                            __syncwarp();
                            warp_arrive(bars + 8 * (BAR_HW + (4 * i + n == 7)));
                        }
                        if (!i && !n && !wg) PROFS(77);
                    }
                }
                if (t == 0) PROF(5 + 25 * wg);
            } else {
                mbar_wait(bars + 8 * BAR_S1, 0);
            }
        }
        if (!main_cta) {
            if (wg) mbar_wait(bars + 8 * BAR_WR, 0);
            fence_proxy_async_smem();
        }
#pragma unroll 1
        for (int ps = wg; ps < 1 + 2 * wg; ps++) {
            if (ps != 1) {
                if (!ps) mbar_wait(bars + 8 * BAR_U, 0);
                if (t == 0) PROF(ps ? 7 : 23);
                radix8(sb, ps, w, lane, 5 + wg);
                if (t == 0) PROF(ps ? 24 : 22);
                if (ps) break;
                bar_sync(5, 128);
                if (FPOS & 1) fence_proxy_async_smem();
            }
            mbar_wait(bars + 8 * (BAR_C + ps), 0);
            phase_c(sb, ps, b + ps == 0, w, lane);
        }
        if (wg == 0) {
            __syncwarp();
            warp_arrive(bars + 8 * BAR_WR);
            if (main_cta) {
                float acc[2][64];
                ring_steps<1>(acc, sb, bars + 8 * BAR_FULL, 31 - LEAD, NS, SLOT_OF(32), 1, 3, 0, 32);
                auto full = [&](int k) { mbar_wait(bars + 8 * (BAR_FULL + SLOT_OF(k)), k > 62); PROFT(k); };
                constexpr int HL = VK == 64 ? 63 : 65;
                auto hstep = [&](int k, int i) {
                    const uint64_t da = make_desc(SLOT_OF(k) * SLOT + i * 8192, 2048, 256, 3), db = make_desc(SLOT_OF(k) * SLOT + 16384, 16, 1024);
                    if (!(LEAD && i && k == HL)) wgmma_fence();
#pragma unroll
                    for (int j = 0; j < 4; j++) wgmma_n128<1, 0>(acc[i], da + 32 * j, db + 2 * j, 1);
                };
                auto vstep = [&](int k, int i) {
                    const uint64_t da = make_desc(OFF_U - i * 32768 + k * 8192, 16, 1024), db = make_desc(SLOT_OF(VK + (k >> 1)) * SLOT + (k & 1) * 16384, 8192, 1024);
                    if (k || !i || LEAD) wgmma_fence();
#pragma unroll
                    for (int j = 0; j < 4; j++) wgmma_n128<0, 1>(acc[i], da + 2 * j, db + 128 * j, 1);
                };
                __syncwarp();
                if (LEAD) {
                    full(62);
                    hstep(62, 0);
                    wgmma_commit();
                    wgmma_wait<1>();
                    warp_arrive(bars + 8 * (BAR_EMPTY + SLOT_OF(61)));
                }
                if (VK == 64) {
                    full(63);
                    hstep(63, 0);
                }
                bar_sync(4, 256);
                full(VK);
                vstep(0, 0);
                vstep(1, 0);
                if (VK == 63) {
                    full(64);
                    vstep(2, 0);
                    vstep(3, 0);
                }
                const CUtensorMap* maps = (const CUtensorMap*)kept(3);
                const uint32_t ob = sb + OFF_U + w * 2048, oa = ob + g * 256 + (((q >> 1) ^ (2 * g & 6)) << 4) + (q & 1) * 8;
#pragma unroll
                for (int i = 0; i < 2; i++) {
                    uint4 e[8];
                    const uint2 sc = lds64u(sb + OFF_SC + (64 * i + 16 * w + 2 * g) * 4);
                    bar_sync(8 + i, 256);
#pragma unroll
                    for (int j = 0; j < 8; j++) e[j] = lds128u(sb + OFF_HS + i * 16384 + (j >> 2) * 8192 + w * 2048 + (j & 3) * 512 + lane * 16);
                    if (i) wgmma_wait<0>();
                    else {
                        full(65);
                        if (VK == 64) {
                            vstep(2, 0);
                            vstep(3, 0);
                        } else hstep(65, 0);
                        wgmma_commit();
                        if (LEAD) hstep(62, 1);
                        hstep(HL, 1);
                        if (!LEAD) vstep(0, 1);
                        wgmma_commit();
                        wgmma_wait<1>();
                    }
#pragma unroll
                    for (int o = 0; o < 64; o++) asm volatile("" : "+f"(acc[i][o]) :: "memory");
                    if (tid == 0) PROF(17 + i);
                    if (tid == 96 && i) PROFG(20);
#pragma unroll
                    for (int c = 0; c < 4; c++) {
#pragma unroll
                        for (int j = 0; j < 8; j++) {
                            const int o = 16 * c + 2 * j;
                            const uint4 e4 = e[2 * c + (j >> 2)];
                            const uint32_t ev = (j & 2) ? ((j & 1) ? e4.w : e4.z) : ((j & 1) ? e4.y : e4.x);
                            const float f = __uint_as_float((j & 1) ? sc.y : sc.x);
                            sts64((oa ^ ((j >> 1) << 5) ^ ((j & 1) * 144)) + c * 8192 - i * 32768, fmaf(f, acc[i][o], bf_lo(ev)), fmaf(f, acc[i][o + 1], bf_hi(ev)));
                        }
                        if (!i && c >= VFIRST && c < 3 + LEAD) {
                            vstep(c + 1 - LEAD, 1);
                            if (c == 2 + LEAD) wgmma_commit();
                        }
                        fence_proxy_async_smem();
                        __syncwarp();
                        if (elect()) tma_store_3d(maps + 9, ob + c * 8192 - i * 32768, 128 * dt + 32 * c, 128 * (tc & 1) + 64 * i + 16 * w, tc >> 1);
                        __syncwarp();
                        if (!i && c < VFIRST && c < 3 + LEAD) {
                            vstep(c + 1 - LEAD, 1);
                            if (c == 2 + LEAD) wgmma_commit();
                        }
                    }
                }
                if (elect()) {
                    bulk_commit();
                    bulk_wait_read();
                }
                if (tid == 0) PROF(19);
                if (tid == 96) { PROF(20); PROFG(4); }
            }
        } else {
            __syncwarp();
            if (tid == 224) PROFG(16);
            if (main_cta) {
                float gs[16];
                uint32_t dk[16], tv[4][4];
#pragma unroll
                for (int j = 0; j < 16; j++) gs[j] = __ldcg(g_gp + (16 * (tc >> 1) + j) * 256 + 128 * (tc & 1) + t);
#pragma unroll
                for (int j = 0; j < 16; j++) dk[j] = ldg32u(P.dskip + 128 * dt + 8 * j + 2 * q);
                const int m0 = ((t >> 2) & 14) + (t >> 6), c0 = 4 * ((t ^ (t >> 3)) & 7);
#pragma unroll
                for (int j = 0; j < 16; j++) {
                    const float a = (float)((j & 3) || c0 ? c0 + (j & 3) : -96) * ((float)(128 * (tc & 1) + 4 * (j & 12) + m0) * 0.024543692606170260f);
                    tv[j >> 2][j & 3] = pack2(__cosf(a), -__sinf(a));
                }
#pragma unroll
                for (int j = 0; j < 4; j++) gs[j] = (gs[j] + gs[j + 4]) + (gs[j + 8] + gs[j + 12]);
                gs[0] = (gs[0] + gs[1]) + (gs[2] + gs[3]);
                const float gg = bf_round(__fdividef(1.f, 1.f + __expf(-bf_round(gs[0])))), og = bf_round(1.f - gg), o2 = fmaxf(2.f * og, 0x1p-40f);
                sts32(sb + OFF_SC + 4 * t, __float_as_uint(o2));
                sts32(sb + OFF_SC + 512 + 4 * t, pack2(__fdividef(gg, o2), og));
                bar_sync(6, 128);
                if (t == 0) PROFX(95);
                auto sign = [](uint32_t n) { return (((n + 1) & 2) << 30) | ((n & 2) << 14); };
                const uint32_t sel = (t & 64) ? 0x1032 : 0x3210;
#pragma unroll
                for (int e = 1; e >= 0; e--) {
                    uint32_t f[4];
#pragma unroll
                    for (int j = 0; j < 4; j++) f[j] = lds16(sb + OFF_SC + 512 + (64 * e + 16 * j + m0) * 4) * 0x10001u;
                    mbar_wait(bars + 8 * (e ? BAR_HD + 1 : BAR_U), !e);
#pragma unroll
                    for (int j = 0; j < 16; j++) {
                        const int k = j & 3, r = j >> 2;
                        uint32_t o[4];
#pragma unroll
                        for (int u = 0; u < 4; u++) {
                            uint32_t v = tv[r][u];
                            if (u == 0 && k < 2 && !c0) v = k ? 0x3f80u : 0x3f003f00u | (t & 64) << 25;
                            if (e) v = ((u & 1) ? __byte_perm(v, 0, 0x1032) : v) ^ sign(u);
                            o[u] = bf_mul2((k & 1) ? __byte_perm(v, 0, sel) : v, f[r] ^ sign(k * m0));
                        }
                        sts128u(sb + OFF_U - e * 32768 + (4 * k + r) * 2048 + t * 16, o[0], o[1], o[2], o[3]);
                        if (P_T && (j & N_T) == N_T) pause(P_T);
                    }
                }
                fence_proxy_async_smem();
                bar_arrive(4, 256);
                if (t == 0) PROF(16);
                const uint32_t xa = sb + OFF_HS + (16 * w + (lane & 15)) * 128 + (((lane >> 4) ^ (lane & 7)) << 4);
#pragma unroll
                for (int e = 0; e < 2; e++) {
                    const uint2 u = lds64u(sb + OFF_SC + 512 + (64 * e + 16 * w + 2 * g) * 4);
                    const uint32_t o0 = __byte_perm(u.x, 0, 0x3232), o1 = __byte_perm(u.y, 0, 0x3232);
                    uint32_t x[8][4];
                    mbar_wait(bars + 8 * (BAR_W + e), 1);
#pragma unroll
                    for (int j = 0; j < 8; j++) {
                        ldsm_x4(x[j], (xa ^ ((j & 3) << 5)) + e * 16384 + (j >> 2) * 8192);
                        if (P_SK && (j & 1)) pause(P_SK);
                    }
#pragma unroll
                    for (int j = 0; j < 8; j++) {
#pragma unroll
                        for (int c = 0; c < 4; c++) x[j][c] = bf_mul2(bf_mul2(x[j][c], dk[2 * j + (c >> 1)]), (c & 1) ? o1 : o0);
                        sts128u(sb + OFF_HS + e * 16384 + (j >> 2) * 8192 + w * 2048 + (j & 3) * 512 + lane * 16, x[j][0], x[j][1], x[j][2], x[j][3]);
                        if (P_SK && (j & 1)) pause(P_SK);
                    }
                    bar_arrive(8 + e, 256);
                    if (t == 0 && !e) PROF(15);
                }
            }
            if (t == 0) {
                const unsigned old = atomicAdd(&g_cnt[CNT_DONE * CS], 1u);
                if (old == 128)
                    asm volatile("st.global.u32 [%0], 0;\nst.global.u32 [%0 + %2], %1;" :: "l"(&g_cnt[CNT_DONE * CS]), "r"((uint32_t)(kept(0) >> 32)), "n"((CNT_EPOCH - CNT_DONE) * CS * 4) : "memory");
            }
        }
    } else {
        const int w = warp - 8;
        if (w == 0) {
            bar_sync(7, 64);
            if (!main_cta || !elect()) return;
            {
                int s = 0; uint32_t ph = 0;
#pragma unroll 1
                for (int k = 5; k < 32; k++) {
                    asm volatile(WAIT_LOOP
                        "cp.async.bulk.tensor.4d.shared::cluster.global.mbarrier::complete_tx::bytes [%3], [%5, {%7, %10, %10, %8}], [%2];\n"
                        "cp.async.bulk.tensor.4d.shared::cluster.global.mbarrier::complete_tx::bytes [%4], [%6, {%7, %10, %10, %9}], [%2];\n"
                        "mbarrier.arrive.expect_tx.shared::cta.b64 _, [%2], 32768;\n}"
                        :: "r"(bars + 8 * (BAR_EMPTY + s)), "r"(ph), "r"(bars + 8 * (BAR_FULL + s + (k >> 4) * 5)), "r"(sb + s * SLOT + 16384), "r"(sb + s * SLOT),
                           "l"(&mapX), "l"(&mapB), "r"((k & 15) * 64), "r"(tc * 64), "r"(dt * 8 + (k >> 4) * 64), "r"(0) : "memory");
                    PROFR(k < 19 ? k - 5 : k - 4);
                    if (++s == (k < 15 ? 5 : NS)) { s = 0; ph ^= 1; }
                }
                auto load_x = [&](int e) {
                    mbar_expect_tx(bars + 8 * (BAR_W + e), 16384);
#pragma unroll
                    for (int i = 0; i < 2; i++) tma_load_5d(sb + OFF_HS + e * 16384 + i * 8192, &mapXe, bars + 8 * (BAR_W + e), 128 * dt + 64 * i, 8 * (tc & 1) + 4 * e, tc >> 1);
                };
                const uint8_t* hp = g_hT + tc * 16384;
                auto load_h = [&](int h) {
                    asm volatile("{\n.reg .pred q;\n.reg .u32 v, m;\nld.volatile.shared.u32 v, [%10];\nsetp.gt.u32 q, v, %8;\nmov.u32 m, 0;\n" WAIT_LOOP
                        "cp.async.bulk.tensor.3d.shared::cluster.global.mbarrier::complete_tx::bytes [%3], [%5, {%9, %7, %8}], [%2];\n"
                        "@q bra LH;\nLV:\nld.volatile.shared.u32 v, [%10];\nadd.u32 m, m, 1;\nsetp.le.u32 q, v, %8;\nsetp.lt.and.u32 q, m, 4194304, q;\n@q bra LV;\nLH:\n"
                        "cp.async.bulk.shared::cluster.global.mbarrier::complete_tx::bytes [%4], [%6], 16384, [%2];\n"
                        "mbarrier.arrive.expect_tx.shared::cta.b64 _, [%2], 32768;\n}\n}"
                        :: "r"(bars + 8 * (BAR_EMPTY + s)), "r"(ph), "r"(bars + 8 * (BAR_FULL + s)), "r"(sb + s * SLOT + 16384), "r"(sb + s * SLOT),
                           "l"(&mapCre + (h & 1)), "l"(hp), "r"(dt * 128), "r"(h >> 1), "r"(0), "r"(sb + OFF_KEPT + 32) : "memory");
                    PROFR(h + (h < VK - 32 ? 28 : 30));
                    hp += 16 * 16384;
                    if (h == K_XE - 32) load_x(0);
                    if (++s == NS) { s = 0; ph ^= 1; }
                };
#pragma unroll 1
                for (int h = 0; h < VK - 32; h++) load_h(h);
                {
                        mbar_wait(bars + 8 * (BAR_F + 2), 0);
#pragma unroll
                        for (int i = 0; i < 2; i++) {
                            const uint32_t pb = bars + 8 * (BAR_XC + i), full = bars + 8 * (BAR_FULL + SLOT_OF(VK + i)), st = sb + SLOT_OF(VK + i) * SLOT;
                            uint32_t rb;
                            asm("mapa.shared::cluster.u32 %0, %1, %2;" : "=r"(rb) : "r"(pb), "r"(~b & 1));
                            asm volatile(WAIT_LOOP "mbarrier.arrive.shared::cluster.b64 _, [%2];\n}" :: "r"(bars + 8 * (BAR_EMPTY + SLOT_OF(VK + i))), "r"(ph), "r"(rb) : "memory");
                            asm volatile(WAIT_LOOP "cp.async.bulk.tensor.3d.shared::cluster.global.mbarrier::complete_tx::bytes.multicast::cluster [%2], [%3, {%5, %6, %7}], [%4], %8;\n}"
                                :: "r"(pb), "r"(1), "r"(st + (b & 1) * 16384), "l"(&mapV), "r"(full), "r"(0), "r"(i * 128 + (b & 1) * 64), "r"((tc >> 1) * 16 + dt * 2), "h"((uint16_t)3) : "memory");
                            mbar_expect_tx(full, SLOT);
                            PROFR(VK - 4 + i);
                        }
                    }
                if (VK == 63) { s = SLOT_OF(65); load_h(31); }
                load_x(1);
            }
        } else {
            const unsigned epoch = load_epoch();
            bar_sync(0, 256);
            if (w == 1) {
                bar_arrive(7, 64);
                if (!elect()) return;
                {
                    if (main_cta) {
                        pause(T_XS);
                        bulk_load(sb + OFF_GW, P.gate_w + (b & 15) * 64, 128, bars + 8 * BAR_XC);
#pragma unroll 1
                        for (int c = 0; c < 4; c++) {
                            mbar_expect_tx(bars + 8 * (BAR_XC + c), c ? 8192 : 8192 + 128);
                            tma_load_4d(sb + OFF_U + c * 8192, &mapXs, bars + 8 * (BAR_XC + c), (b & 15) * 64, 0, c, b >> 4);
                            pause(P_XS);
                        }
                    }
                    mbar_wait(bars + 8 * BAR_S1, 0);
                    fence_proxy_async_smem();
                    if (main_cta) {
#pragma unroll 1
                        for (int c = 0; c < 4 * UN; c++) {
                            if (c) pause(PACE_U);
                            tma_store_4d(&mapU0, sb + OFF_U + c * (8192 / UN), (b & 15) * 64, UN == 4 ? 32 * (c >> 2) + 16 * (c & 1) : 32 * (c / UN), UN == 4 ? (c >> 1) & 1 : c % UN, b >> 4);
                        }
                        bulk_store(g_gp + b * 256, sb + OFF_GW, 1024);
                        bulk_commit();
                        bulk_wait0();
                        signal_counter(&g_cnt[CNT_U * CS]);
                    }
                    PROF(9);
                    mbar_expect_tx(bars + 8 * BAR_U, 32768);
                    wait_counter(&g_cnt[CNT_U * CS + (b & (NREP - 1)) * RS], epoch * 128);
                    PROF(11);
#pragma unroll
                    for (int i = 0; i < 8; i++) {
                        if (PACE_L && i && !(i & 1)) pause(PACE_L);
                        tma_load_4d(sb + OFF_U + i * 4096, &mapU2, bars + 8 * BAR_U, 0, 0, (i & 3) * 4, b == 128 ? 1 : b == 0 ? 0 : 2 * b + (i >> 2));
                    }
                    if (main_cta) {
#pragma unroll 1
                        for (int i = 0; i < 2; i++) {
#pragma unroll 1
                            for (int j = 0; j < 2 * HN; j++) {
                                const int hf = j / HN, jj = j % HN;
                                if (j) pause(i ? PACE_HB : PACE_HA);
                                if (j == 0 || j == HS0 * HN / 4) mbar_wait(bars + 8 * (BAR_HW + (j > 0)), i);
                                if (j == 0 && !HF) fence_proxy_async_smem();
                                tma_store_3d(&mapH, sb + OFF_HS + hf * (16384 + i * 18432) + jj * (16384 / HN), 0, 2 * tc + hf, (dt + 8 * i) * 16 + jj * (16 / HN));
                            }
                            bulk_commit();
                            bulk_wait0();
#pragma unroll
                            for (int r = 0; r < NREPH; r++)
                                asm volatile("red.relaxed.gpu.global.add.u64 [%0], %1;" :: "l"(&g_cnt[(CNT_H + 2 * i + (tc >> 3)) * CS + r * RS]), "l"(1ull << (8 * dt)) : "memory");
                            mbar_arrive(bars + 8 * (BAR_HD + i));
                            PROF(i ? 6 : 26);
                            const unsigned* cp = &g_cnt[(CNT_H + 2 * i + (tc & 1)) * CS + ((b >> 1) & (NREPH - 1)) * RS];
#pragma unroll 1
                            for (unsigned n = 0; n < SPIN_LIMIT; n++) {
                                uint64_t v;
                                asm volatile("ld.relaxed.gpu.global.u64 %0, [%1];" : "=l"(v) : "l"(cp) : "memory");
                                v = epoch * 0x0808080808080808ull - v;
                                sts32(sb + OFF_KEPT + 32, (__clzll(__brevll(v)) >> 3) + 8 * i);
                                if (!v) break;
                                if (P_HP) pause(P_HP);
                            }
                            PROF(1 + i);
                        }
                    }
                }
            } else {
                const int ld = (1026 * cls) >> 7, lm = (1026 * ((256 - cls) & 255)) >> 7;
                if (elect() && main_cta) {
                    if (w == 3) {
                        pause(T_W);
#pragma unroll 1
                        for (int i = 0; i < 8; i++) {
                            tma_prefetch_4d(&mapWr + (i & 1), 0, (i & 2) ? lm : ld, i >> 2, 0);
                            pause(200);
                        }
                    } else {
                        pause(T_BA + D_XS * tc);
                        if (tc > 4) tma_prefetch_4d(&mapB, tc * 64, 0, 0, dt * 8);
                        pause(T_B2);
                        bulk_prefetch_l2(((b & 1) ? P.b_im : P.b_re) + (64 + (b >> 1)) * 8192, 16384);
                        pause(T_W0 - D_XS * tc);
                    }
                }
#pragma unroll 1
                for (int ps = 0; ps < 2; ps++) {
                    const uint32_t wb = sb + OFF_W + (1 - ps) * 18432;
                    if (w == 2 && elect()) {
                        const uint32_t bw = bars + 8 * (BAR_W + ps);
                        if (ps && main_cta) mbar_wait(bars + 8 * BAR_HD, 0);
                        mbar_expect_tx(bw, ps ? 18432 : 18432 + 8192);
#pragma unroll 1
                        for (int i = 0; i < 4; i++) {
                            tma_load_4d(wb + (i >> 1) * 4608 + (i & 1) * 9216, &mapWr + (i & 1), bw, 0, i < 2 ? ld : lm, (i < 2 || b == 0) ? ps : 1 - ps, 0);
                            pause(P_W);
                        }
                        if (!ps) bulk_load(sb + OFF_F, c_tab + 8192, 8192, bw);
                        PROFX(85 + ps);
                    }
                    if (w == 3 && ps && main_cta && elect()) {
#pragma unroll 1
                        for (int i = 0; i < 8; i++) {
                            bulk_prefetch_l2(((b & 1) ? P.c_im : P.c_re) + (size_t)(b >> 1) * 16384 + i * 2048, 4096);
                            pause(P_C);
                        }
                    }
                    __syncwarp();
                    mbar_wait(bars + 8 * (BAR_W + ps), 0);
                    if (tid == 320) PROF(ps ? 31 : 10);
#pragma unroll 1
                    for (int u = 0; u < 4; u++) {
                        const int row = 2 * (w - 2) + (u >> 1), pl = u & 1;
                        const uint32_t dp = wb + pl * 9216 + row * 1152, mp = wb + pl * 9216 + 4608 + ((b == 0 && ps == 0) ? (4 - row) & 3 : 3 - row) * 1152;
                        const uint32_t od = dp + ((1026 * cls) & 127), om = mp + ((1026 * (256 - cls)) & 127);
                        uint32_t v[4][8], o[4][4];
#pragma unroll
                        for (int i = 0; i < 8; i++) {
                            const uint4 r = lds128u((i < 4 ? (od & ~15u) + 16 * lane + (i >> 1) * 512 : ((om + 1010) & ~15u) - 16 * lane - ((i >> 1) & 1) * 512) + (i & 1) * 16);
                            uint32_t* d = &v[i >> 1][4 * (i & 1)];
                            d[0] = r.x; d[1] = r.y; d[2] = r.z; d[3] = r.w;
                            if ((P_W0 || P_W1) && (i & 1) && i < 7) pause(ps ? P_W1 : P_W0);
                        }
                        const uint32_t e0 = lds16(om), e1 = lds16(od + 1024);
                        auto fwd = [&](int ws) {
#pragma unroll
                            for (int k = 0; k < 8; k++) o[k >> 2][k & 3] = __byte_perm(v[k >> 2][ws + (k & 3)], v[k >> 2][ws + (k & 3) + 1], (cls & 1) ? 0x5432 : 0x3210);
                        };
                        auto mir = [&](int ws) {
#pragma unroll
                            for (int k = 8; k < 16; k++) o[k >> 2][k & 3] = __byte_perm(v[k >> 2][ws + 3 - (k & 3)], v[k >> 2][ws + 4 - (k & 3)], (cls & 1) ? 0x1032 : 0x3254);
                        };
                        switch ((cls >> 1) & 3) { case 0: fwd(0); break; case 1: fwd(1); break; case 2: fwd(2); break; default: fwd(3); }
                        switch (((1 - cls) >> 1) & 3) { case 0: mir(0); break; case 1: mir(1); break; case 2: mir(2); break; default: mir(3); }
                        if (lane == 0) {
                            o[0][0] = pack2(fmaf(pl ? -0.5f : 0.5f, bf_lo(e0), 0.5f * bf_lo(o[0][0])), bf_hi(o[0][0]));
                            o[2][0] = pack2(fmaf(pl ? -0.5f : 0.5f, bf_lo(e1), 0.5f * bf_lo(o[2][0])), bf_hi(o[2][0]));
                        }
                        __syncwarp();
#pragma unroll
                        for (int i = 0; i < 4; i++)
                        {
                            sts128u((i < 2 ? dp : mp) + (i & 1) * 512 + ((lane * 16) ^ ((lane << 1) & 48)), o[i][0], o[i][1], o[i][2], o[i][3]);
                            if ((P_W0 || P_W1) && (i & 1)) pause(ps ? P_W1 : P_W0);
                        }
                    }
                    if (ps) fence_proxy_async_smem();
                    mbar_arrive(bars + 8 * (BAR_C + ps));
                    if (tid == 320) PROF(ps ? 12 : 28);
                }
                if (!elect()) return;
                if (w == 2) {
                    {
#pragma unroll 1
                        for (int i = 0; i < 8; i++) {
                            if (!(i & 3)) { mbar_wait(bars + 8 * BAR_VW, i >> 2); if (!i && !HF) fence_proxy_async_smem(); }
                            else pause(PACE_V);
                            if (!(real_cls && (i & 1))) tma_store_4d(&mapU2, sb + OFF_U + (i & 1) * 16384 + (i >> 1) * 4096, 0, 0, (i >> 1) * 4, b == 128 ? 1 : 2 * b + (i & 1));
                        }
                        bulk_commit();
                        bulk_wait_read();
                        mbar_arrive(bars + 8 * BAR_U);
                        bulk_wait0();
                        signal_counter(&g_cnt[CNT_V * CS]);
                        PROF(13);
                        if (main_cta) {
                            wait_counter(&g_cnt[CNT_V * CS + (b & (NREP - 1)) * RS], epoch * 129);
                            mbar_arrive(bars + 8 * (BAR_F + 2));
                            PROF(14);
                        }
                    }
                }
            }
        }
    }
}

typedef CUresult (*PFN_encodeTiled)(CUtensorMap*, CUtensorMapDataType, cuuint32_t, void*, const cuuint64_t*, const cuuint64_t*,
                                    const cuuint32_t*, const cuuint32_t*, CUtensorMapInterleave, CUtensorMapSwizzle,
                                    CUtensorMapL2promotion, CUtensorMapFloatOOBfill);

static CUtensorMap make_map(PFN_encodeTiled enc, const void* ptr, int rank, const cuuint64_t* dims, const cuuint64_t* strides, const cuuint32_t* box,
                            CUtensorMapSwizzle sw = CU_TENSOR_MAP_SWIZZLE_128B, CUtensorMapDataType dt = CU_TENSOR_MAP_DATA_TYPE_BFLOAT16) {
    CUtensorMap m;
    cuuint32_t es[5] = {1, 1, 1, 1, 1};
    enc(&m, dt, rank, (void*)ptr, dims, strides, box, es, CU_TENSOR_MAP_INTERLEAVE_NONE,
        sw, CU_TENSOR_MAP_L2_PROMOTION_L2_128B, CU_TENSOR_MAP_FLOAT_OOB_FILL_NONE);
    return m;
}

extern "C" void kernel_launch(void* const* d_in, const int* in_sizes, int n_in, void* d_out, int out_size) {
    const bf16* x = (const bf16*)d_in[0];
    const bf16* wr = (const bf16*)d_in[1];
    const bf16* wi = (const bf16*)d_in[2];
    const bf16* Bre = (const bf16*)d_in[6];
    const bf16* Bim = (const bf16*)d_in[7];
    const bf16* Cre = (const bf16*)d_in[8];
    const bf16* Cim = (const bf16*)d_in[9];

    void* fn = nullptr;
    cudaDriverEntryPointQueryResult st;
    cudaGetDriverEntryPoint("cuTensorMapEncodeTiled", &fn, cudaEnableDefault, &st);
    PFN_encodeTiled enc = (PFN_encodeTiled)fn;
    void *p_hT, *p_U;
    cudaGetSymbolAddress(&p_hT, g_hT);
    cudaGetSymbolAddress(&p_U, g_U);

    Params P;
    P.lam_re = (const bf16*)d_in[4]; P.lam_im = (const bf16*)d_in[5]; P.log_dt = (const bf16*)d_in[10];
    P.dskip = (const bf16*)d_in[11]; P.gate_w = (const bf16*)d_in[12]; P.c_re = Cre; P.c_im = Cim; P.b_re = Bre; P.b_im = Bim; P.x = x;
    P.swapB = Bim < Bre;
    for (int i = 0; i < 130; i++) {
        const int cl = i >> 1;
        const int role = cl < 4 ? 32 + 8 * cl : cl < 36 ? ((cl - 4) & 24) + ((cl - 5) & 7) : cl < 64 ? 33 + 8 * ((cl - 36) / 7) + (cl - 30) % 7 : cl;
        const int b = role * 2 + (i & 1), dt = ((b >> 1) & 4) + (b >> 5), tc = 4 * ((b >> 1) & 3) + ((b >> 3) & 2) + (b & 1);
        P.tile[i] = b < 128 ? make_int2(dt * 8, tc * 64) : make_int2(INT_MIN, (b & 1) * 64);
    }

    CUtensorMap mB, mX, mCre, mCim, mXs, mU0, mV, mU2, mXe, mO, mWr, mWi, mH;
    {
        cuuint64_t d[4] = {64, 2052, 2, 4}, s[3] = {128, 262656, 525312};
        cuuint32_t bx[4] = {64, 9, 1, 4};
        mWr = make_map(enc, wr, 4, d, s, bx, CU_TENSOR_MAP_SWIZZLE_NONE);
        mWi = make_map(enc, wi, 4, d, s, bx, CU_TENSOR_MAP_SWIZZLE_NONE);
    }
    {
        cuuint64_t d[3] = {128, 32, 256}, s[2] = {1024, 32768};
        cuuint32_t bx[3] = {128, 1, 16 / HN};
        mH = make_map(enc, p_hT, 3, d, s, bx, CU_TENSOR_MAP_SWIZZLE_NONE, CU_TENSOR_MAP_DATA_TYPE_UINT64);
    }
    {
        const bf16* lo = P.swapB ? Bim : Bre; const bf16* hi = P.swapB ? Bre : Bim;
        cuuint64_t d[4] = {1024, 8, 2, 128}, s[3] = {2048, (cuuint64_t)((const char*)hi - (const char*)lo), 16384};
        cuuint32_t bx[4] = {64, 8, 2, 8};
        mB = make_map(enc, lo, 4, d, s, bx);
    }
    {
        cuuint64_t d[4] = {1024, 2, 4, 976}, s[3] = {2048, 32 * 2048, 2 * 2048};
        cuuint32_t bx[4] = {64, 2, 4, 16};
        mX = make_map(enc, x, 4, d, s, bx);
    }
    {
        cuuint64_t d[3] = {64, 1024, 16}, s[2] = {2048, 128};
        cuuint32_t bx[3] = {64, 128, 1};
        mCre = make_map(enc, Cre, 3, d, s, bx);
        mCim = make_map(enc, Cim, 3, d, s, bx);
    }
    {
        cuuint64_t d[3] = {64, 256, 128}, s[2] = {16384, 128};
        cuuint32_t bx[3] = {64, 64, 2};
        mV = make_map(enc, p_U, 3, d, s, bx);
    }
    {
        cuuint64_t d[5] = {1024, 8, 2, 16, 8}, s[4] = {16 * 2048, 8 * 2048, 128 * 2048, 2048};
        cuuint32_t bx[5] = {64, 8, 2, 4, 1};
        mXe = make_map(enc, x, 5, d, s, bx);
    }
    {
        cuuint64_t d[3] = {1024, 256, 8}, s[2] = {8 * 4096, 4096};
        cuuint32_t bx[3] = {32, 16, 1};
        mO = make_map(enc, d_out, 3, d, s, bx, CU_TENSOR_MAP_SWIZZLE_128B, CU_TENSOR_MAP_DATA_TYPE_FLOAT32);
    }
    {
        cuuint64_t d[4] = {1024, 64, 4, 8}, s[3] = {32 * 2048, 8 * 2048, 2048};
        cuuint32_t bx[4] = {64, 64, 1, 1};
        mXs = make_map(enc, x, 4, d, s, bx);
    }
    {
        cuuint64_t d[4] = {1024, 128, 2, 8}, s[3] = {32768, 16384, 2048};
        cuuint32_t bx[4] = {64, UN == 4 ? 16 : 32, UN == 1 ? 2 : 1, 1};
        mU0 = make_map(enc, p_U, 4, d, s, bx);
    }
    {
        cuuint64_t d[4] = {64, 8, 16, 256}, s[3] = {2048, 128, 16384};
        cuuint32_t bx[4] = {64, 8, 4, 1};
        mU2 = make_map(enc, p_U, 4, d, s, bx);
    }
    cudaFuncSetAttribute(fused_kernel, cudaFuncAttributeMaxDynamicSharedMemorySize, SMEM_BYTES);
    fused_kernel<<<130, 384, SMEM_BYTES, cudaStreamPerThread>>>(mB, mX, mXs, mU0, mU2, mXe, mCre, mCim, mV, mO, mWr, mWi, mH, P);
}
```

```cpp
#include <cuda_runtime.h>
#include <cuda_bf16.h>
#include <cuda.h>
#include <stdint.h>
#include <limits.h>

typedef __nv_bfloat16 bf16;

__device__ const __align__(128) uint32_t c_tab[10240] = {
0x3f803f80,0xbf803f80,0x3f803f80,0xbf803f80,0x3f803f80,0xbf803f80,0x3f803f80,0xbf803f80,0x3f803f80,0xbf803f80,0x3f803f80,0xbf803f80,
0x3f803f80,0xbf803f80,0x3f803f80,0xbf803f80,0x3f7f3f80,0xbdc98000,0x3f223f35,0xbf46bf35,0x3f753f7b,0xbe95be48,0x3ef13f0e,0xbf62bf55,
0x3f623f6d,0xbef1bec4,0x3e953ec4,0xbf75bf6d,0x3f463f55,0xbf22bf0e,0x3dc93e48,0xbf7fbf7b,0x3f7b3f80,0xbe488000,0xbe480000,0xbf7bbf80,
0x3f553f6d,0xbf0ebec4,0xbf0ebec4,0xbf55bf6d,0x3f0e3f35,0xbf55bf35,0xbf55bf35,0xbf0ebf35,0x3e483ec4,0xbf7bbf6d,0xbf7bbf6d,0xbe48bec4,
0x3f753f80,0xbe958000,0xbf62bf35,0xbef1bf35,0x3f223f55,0xbf46bf0e,0xbf7fbf7b,0x3dc9be48,0x3dc93ec4,0xbf7fbf6d,0xbf46bf6d,0x3f223ec4,
0xbef1be48,0xbf62bf7b,0xbe95bf0e,0x3f753f55,0x3f6d3f80,0xbec48000,0xbf6dbf80,0x3ec48000,0x3ec43f35,0xbf6dbf35,0xbec4bf35,0x3f6d3f35,
0xbec40000,0xbf6dbf80,0x3ec40000,0x3f6d3f80,0xbf6dbf35,0xbec4bf35,0x3f6d3f35,0x3ec43f35,0x3f623f80,0xbef18000,0xbe95bf35,0x3f753f35,
0x3dc93f0e,0xbf7fbf55,0x3f223e48,0x3f463f7b,0xbf46bec4,0xbf22bf6d,0x3f7f3f6d,0xbdc93ec4,0xbf75bf7b,0x3e95be48,0x3ef13f55,0xbf62bf0e,
0x3f553f80,0xbf0e8000,0x3f0e0000,0x3f553f80,0xbe483ec4,0xbf7bbf6d,0x3f7b3f6d,0xbe483ec4,0xbf7bbf35,0xbe48bf35,0x3e483f35,0xbf7bbf35,
0xbf0ebf6d,0x3f553ec4,0xbf55bec4,0xbf0ebf6d,0x3f463f80,0xbf228000,0x3f7f3f35,0x3dc93f35,0xbef13e48,0xbf62bf7b,0x3e953f55,0xbf75bf0e,
0xbf75bf6d,0x3e95bec4,0xbf62bec4,0xbef1bf6d,0x3dc9bf0e,0x3f7f3f55,0xbf22bf7b,0x3f463e48,0x3f353f80,0xbf358000,0x3f353f80,0xbf358000,
0xbf350000,0xbf35bf80,0xbf350000,0xbf35bf80,0xbf35bf80,0x3f358000,0xbf35bf80,0x3f358000,0x3f350000,0x3f353f80,0x3f350000,0x3f353f80,
0x3f223f80,0xbf468000,0xbdc93f35,0xbf7fbf35,0xbf62be48,0xbef1bf7b,0xbf75bf55,0x3e95bf0e,0xbe95bf6d,0x3f753ec4,0x3ef1bec4,0x3f623f6d,
0x3f7f3f0e,0x3dc93f55,0x3f463f7b,0xbf223e48,0x3f0e3f80,0xbf558000,0xbf550000,0xbf0ebf80,0xbf7bbec4,0xbe48bf6d,0xbe48bf6d,0x3f7b3ec4,
0x3e48bf35,0x3f7b3f35,0x3f7b3f35,0xbe483f35,0x3f553f6d,0xbf0e3ec4,0xbf0e3ec4,0xbf55bf6d,0x3ef13f80,0xbf628000,0xbf75bf35,0x3e95bf35,
0xbf7fbf0e,0x3dc9bf55,0x3f46be48,0x3f223f7b,0x3f22bec4,0x3f463f6d,0x3dc93f6d,0xbf7fbec4,0x3e953f7b,0xbf75be48,0xbf62bf55,0x3ef1bf0e,
0x3ec43f80,0xbf6d8000,0xbec4bf80,0x3f6d8000,0xbf6dbf35,0x3ec4bf35,0x3f6d3f35,0xbec43f35,0x3f6d0000,0x3ec43f80,0xbf6d0000,0xbec4bf80,
0xbec43f35,0xbf6dbf35,0x3ec4bf35,0x3f6d3f35,0x3e953f80,0xbf758000,0x3ef1bf35,0x3f623f35,0xbf46bf55,0x3f22bf0e,0x3dc93f7b,0xbf7fbe48,
0x3f7f3ec4,0xbdc93f6d,0xbf22bf6d,0x3f46bec4,0xbf623e48,0xbef1bf7b,0x3f753f0e,0xbe953f55,0x3e483f80,0xbf7b8000,0x3f7b0000,0x3e483f80,
0xbf0ebf6d,0x3f55bec4,0xbf553ec4,0xbf0ebf6d,0x3f553f35,0xbf0e3f35,0x3f0ebf35,0x3f553f35,0xbf7bbec4,0x3e48bf6d,0xbe483f6d,0xbf7bbec4,
0x3dc93f80,0xbf7f8000,0x3f463f35,0xbf223f35,0xbe95bf7b,0x3f75be48,0xbf62bf0e,0x3ef1bf55,0x3ef13f6d,0xbf623ec4,0x3f753ec4,0xbe953f6d,
0xbf22bf55,0x3f46bf0e,0xbf7fbe48,0x3dc9bf7b,0x3f80,0xbf808000,0x3f80,0xbf808000,0xbf80,0x3f808000,0xbf80,0x3f808000,
0x3f80,0xbf808000,0x3f80,0xbf808000,0xbf80,0x3f808000,0xbf80,0x3f808000,0xbdc93f80,0xbf7f8000,0xbf463f35,0xbf22bf35,
0x3e95bf7b,0x3f753e48,0x3f62bf0e,0x3ef13f55,0xbef13f6d,0xbf62bec4,0xbf753ec4,0xbe95bf6d,0x3f22bf55,0x3f463f0e,0x3f7fbe48,0x3dc93f7b,
0xbe483f80,0xbf7b8000,0xbf7b0000,0x3e48bf80,0x3f0ebf6d,0x3f553ec4,0x3f553ec4,0xbf0e3f6d,0xbf553f35,0xbf0ebf35,0xbf0ebf35,0x3f55bf35,
0x3f7bbec4,0x3e483f6d,0x3e483f6d,0xbf7b3ec4,0xbe953f80,0xbf758000,0xbef1bf35,0x3f62bf35,0x3f46bf55,0x3f223f0e,0xbdc93f7b,0xbf7f3e48,
0xbf7f3ec4,0xbdc9bf6d,0x3f22bf6d,0x3f463ec4,0x3f623e48,0xbef13f7b,0xbf753f0e,0xbe95bf55,0xbec43f80,0xbf6d8000,0x3ec4bf80,0x3f6d8000,
0x3f6dbf35,0x3ec43f35,0xbf6d3f35,0xbec4bf35,0xbf6d0000,0x3ec4bf80,0x3f6d0000,0xbec43f80,0x3ec43f35,0xbf6d3f35,0xbec4bf35,0x3f6dbf35,
0xbef13f80,0xbf628000,0x3f75bf35,0x3e953f35,0x3f7fbf0e,0x3dc93f55,0xbf46be48,0x3f22bf7b,0xbf22bec4,0x3f46bf6d,0xbdc93f6d,0xbf7f3ec4,
0xbe953f7b,0xbf753e48,0x3f62bf55,0x3ef13f0e,0xbf0e3f80,0xbf558000,0x3f550000,0xbf0e3f80,0x3f7bbec4,0xbe483f6d,0x3e48bf6d,0x3f7bbec4,
0xbe48bf35,0x3f7bbf35,0xbf7b3f35,0xbe48bf35,0xbf553f6d,0xbf0ebec4,0x3f0e3ec4,0xbf553f6d,0xbf223f80,0xbf468000,0x3dc93f35,0xbf7f3f35,
0x3f62be48,0xbef13f7b,0x3f75bf55,0x3e953f0e,0x3e95bf6d,0x3f75bec4,0xbef1bec4,0x3f62bf6d,0xbf7f3f0e,0x3dc9bf55,0xbf463f7b,0xbf22be48,
0xbf353f80,0xbf358000,0xbf353f80,0xbf358000,0x3f350000,0xbf353f80,0x3f350000,0xbf353f80,0x3f35bf80,0x3f358000,0x3f35bf80,0x3f358000,
0xbf350000,0x3f35bf80,0xbf350000,0x3f35bf80,0xbf463f80,0xbf228000,0xbf7f3f35,0x3dc9bf35,0x3ef13e48,0xbf623f7b,0xbe953f55,0xbf753f0e,
0x3f75bf6d,0x3e953ec4,0x3f62bec4,0xbef13f6d,0xbdc9bf0e,0x3f7fbf55,0x3f22bf7b,0x3f46be48,0xbf553f80,0xbf0e8000,0xbf0e0000,0x3f55bf80,
0x3e483ec4,0xbf7b3f6d,0xbf7b3f6d,0xbe48bec4,0x3f7bbf35,0xbe483f35,0xbe483f35,0xbf7b3f35,0x3f0ebf6d,0x3f55bec4,0x3f55bec4,0xbf0e3f6d,
0xbf623f80,0xbef18000,0x3e95bf35,0x3f75bf35,0xbdc93f0e,0xbf7f3f55,0xbf223e48,0x3f46bf7b,0x3f46bec4,0xbf223f6d,0xbf7f3f6d,0xbdc9bec4,
0x3f75bf7b,0x3e953e48,0xbef13f55,0xbf623f0e,0xbf6d3f80,0xbec48000,0x3f6dbf80,0x3ec48000,0xbec43f35,0xbf6d3f35,0x3ec4bf35,0x3f6dbf35,
0x3ec40000,0xbf6d3f80,0xbec40000,0x3f6dbf80,0x3f6dbf35,0xbec43f35,0xbf6d3f35,0x3ec4bf35,0xbf753f80,0xbe958000,0x3f62bf35,0xbef13f35,
0xbf223f55,0xbf463f0e,0x3f7fbf7b,0x3dc93e48,0xbdc93ec4,0xbf7f3f6d,0x3f46bf6d,0x3f22bec4,0x3ef1be48,0xbf623f7b,0x3e95bf0e,0x3f75bf55,
0xbf7b3f80,0xbe488000,0x3e480000,0xbf7b3f80,0xbf553f6d,0xbf0e3ec4,0x3f0ebec4,0xbf553f6d,0xbf0e3f35,0xbf553f35,0x3f55bf35,0xbf0e3f35,
0xbe483ec4,0xbf7b3f6d,0x3f7bbf6d,0xbe483ec4,0xbf7f3f80,0xbdc98000,0xbf223f35,0xbf463f35,0xbf753f7b,0xbe953e48,0xbef13f0e,0xbf623f55,
0xbf623f6d,0xbef13ec4,0xbe953ec4,0xbf753f6d,0xbf463f55,0xbf223f0e,0xbdc93e48,0xbf7f3f7b,0x3f803f80,0xbf803f80,0x3f803f80,0xbf803f80,
0x3f803f80,0xbf803f80,0x3f803f80,0xbf803f80,0x3f803f80,0xbf803f80,0x3f803f80,0xbf803f80,0x3f803f80,0xbf803f80,0x3f803f80,0xbf803f80,
0xbdc90000,0xbf7fbf80,0xbf46bf35,0xbf22bf35,0xbe95be48,0xbf75bf7b,0xbf62bf55,0xbef1bf0e,0xbef1bec4,0xbf62bf6d,0xbf75bf6d,0xbe95bec4,
0xbf22bf0e,0xbf46bf55,0xbf7fbf7b,0xbdc9be48,0xbf7bbf80,0x3e488000,0x3e480000,0x3f7b3f80,0xbf55bf6d,0x3f0e3ec4,0x3f0e3ec4,0x3f553f6d,
0xbf0ebf35,0x3f553f35,0x3f553f35,0x3f0e3f35,0xbe48bec4,0x3f7b3f6d,0x3f7b3f6d,0x3e483ec4,0x3e950000,0x3f753f80,0x3ef13f35,0xbf62bf35,
0x3f463f0e,0x3f223f55,0xbdc93e48,0xbf7fbf7b,0x3f7f3f6d,0x3dc93ec4,0xbf22bec4,0xbf46bf6d,0x3f623f7b,0xbef1be48,0xbf75bf55,0xbe95bf0e,
0x3f6d3f80,0xbec48000,0xbf6dbf80,0x3ec48000,0x3ec43f35,0xbf6dbf35,0xbec4bf35,0x3f6d3f35,0xbec40000,0xbf6dbf80,0x3ec40000,0x3f6d3f80,
0xbf6dbf35,0xbec4bf35,0x3f6d3f35,0x3ec43f35,0xbef10000,0xbf62bf80,0x3f753f35,0x3e953f35,0xbf7fbf55,0xbdc9bf0e,0x3f463f7b,0xbf22be48,
0xbf22bf6d,0x3f463ec4,0xbdc93ec4,0xbf7fbf6d,0x3e95be48,0x3f753f7b,0xbf62bf0e,0xbef1bf55,0xbf55bf80,0x3f0e8000,0xbf0e0000,0xbf55bf80,
0x3e48bec4,0x3f7b3f6d,0xbf7bbf6d,0x3e48bec4,0x3f7b3f35,0x3e483f35,0xbe48bf35,0x3f7b3f35,0x3f0e3f6d,0xbf55bec4,0x3f553ec4,0x3f0e3f6d,
0x3f220000,0x3f463f80,0xbdc9bf35,0x3f7f3f35,0x3f623f7b,0xbef13e48,0x3f753f0e,0x3e953f55,0xbe953ec4,0xbf75bf6d,0x3ef13f6d,0xbf62bec4,
0xbf7fbf55,0x3dc9bf0e,0xbf46be48,0xbf22bf7b,0x3f353f80,0xbf358000,0x3f353f80,0xbf358000,0xbf350000,0xbf35bf80,0xbf350000,0xbf35bf80,
0xbf35bf80,0x3f358000,0xbf35bf80,0x3f358000,0x3f350000,0x3f353f80,0x3f350000,0x3f353f80,0xbf460000,0xbf22bf80,0xbf7fbf35,0x3dc9bf35,
0xbef1bf7b,0x3f623e48,0x3e95bf0e,0x3f753f55,0x3f753ec4,0x3e953f6d,0x3f623f6d,0xbef13ec4,0x3dc93f55,0xbf7fbf0e,0xbf223e48,0xbf46bf7b,
0xbf0ebf80,0x3f558000,0x3f550000,0x3f0e3f80,0x3f7b3ec4,0x3e483f6d,0x3e483f6d,0xbf7bbec4,0xbe483f35,0xbf7bbf35,0xbf7bbf35,0x3e48bf35,
0xbf55bf6d,0x3f0ebec4,0x3f0ebec4,0x3f553f6d,0x3f620000,0x3ef13f80,0xbe953f35,0xbf75bf35,0xbdc93f55,0xbf7fbf0e,0xbf22bf7b,0x3f46be48,
0xbf46bf6d,0x3f22bec4,0x3f7f3ec4,0x3dc93f6d,0x3f753e48,0x3e953f7b,0xbef13f0e,0xbf62bf55,0x3ec43f80,0xbf6d8000,0xbec4bf80,0x3f6d8000,
0xbf6dbf35,0x3ec4bf35,0x3f6d3f35,0xbec43f35,0x3f6d0000,0x3ec43f80,0xbf6d0000,0xbec4bf80,0xbec43f35,0xbf6dbf35,0x3ec4bf35,0x3f6d3f35,
0xbf750000,0xbe95bf80,0x3f623f35,0xbef13f35,0x3f22bf0e,0x3f463f55,0xbf7fbe48,0xbdc9bf7b,0xbdc93f6d,0xbf7fbec4,0x3f46bec4,0x3f223f6d,
0xbef1bf7b,0x3f62be48,0xbe953f55,0xbf75bf0e,0xbe48bf80,0x3f7b8000,0xbf7b0000,0xbe48bf80,0x3f0e3f6d,0xbf553ec4,0x3f55bec4,0x3f0e3f6d,
0xbf55bf35,0x3f0ebf35,0xbf0e3f35,0xbf55bf35,0x3f7b3ec4,0xbe483f6d,0x3e48bf6d,0x3f7b3ec4,0x3f7f0000,0x3dc93f80,0x3f22bf35,0x3f463f35,
0xbf753e48,0xbe95bf7b,0xbef13f55,0xbf62bf0e,0x3f62bec4,0x3ef13f6d,0x3e95bf6d,0x3f753ec4,0xbf463f0e,0xbf22bf55,0xbdc93f7b,0xbf7fbe48,
0x3f80,0xbf808000,0x3f80,0xbf808000,0xbf80,0x3f808000,0xbf80,0x3f808000,0x3f80,0xbf808000,0x3f80,0xbf808000,
0xbf80,0x3f808000,0xbf80,0x3f808000,0xbf7f0000,0x3dc9bf80,0xbf22bf35,0x3f46bf35,0x3f753e48,0xbe953f7b,0x3ef13f55,0xbf623f0e,
0xbf62bec4,0x3ef1bf6d,0xbe95bf6d,0x3f75bec4,0x3f463f0e,0xbf223f55,0x3dc93f7b,0xbf7f3e48,0x3e48bf80,0x3f7b8000,0x3f7b0000,0xbe483f80,
0xbf0e3f6d,0xbf55bec4,0xbf55bec4,0x3f0ebf6d,0x3f55bf35,0x3f0e3f35,0x3f0e3f35,0xbf553f35,0xbf7b3ec4,0xbe48bf6d,0xbe48bf6d,0x3f7bbec4,
0x3f750000,0xbe953f80,0xbf623f35,0xbef1bf35,0xbf22bf0e,0x3f46bf55,0x3f7fbe48,0xbdc93f7b,0x3dc93f6d,0xbf7f3ec4,0xbf46bec4,0x3f22bf6d,
0x3ef1bf7b,0x3f623e48,0x3e953f55,0xbf753f0e,0xbec43f80,0xbf6d8000,0x3ec4bf80,0x3f6d8000,0x3f6dbf35,0x3ec43f35,0xbf6d3f35,0xbec4bf35,
0xbf6d0000,0x3ec4bf80,0x3f6d0000,0xbec43f80,0x3ec43f35,0xbf6d3f35,0xbec4bf35,0x3f6dbf35,0xbf620000,0x3ef1bf80,0x3e953f35,0xbf753f35,
0x3dc93f55,0xbf7f3f0e,0x3f22bf7b,0x3f463e48,0x3f46bf6d,0x3f223ec4,0xbf7f3ec4,0x3dc9bf6d,0xbf753e48,0x3e95bf7b,0x3ef13f0e,0xbf623f55,
0x3f0ebf80,0x3f558000,0xbf550000,0x3f0ebf80,0xbf7b3ec4,0x3e48bf6d,0xbe483f6d,0xbf7b3ec4,0x3e483f35,0xbf7b3f35,0x3f7bbf35,0x3e483f35,
0x3f55bf6d,0x3f0e3ec4,0xbf0ebec4,0x3f55bf6d,0x3f460000,0xbf223f80,0x3f7fbf35,0x3dc93f35,0x3ef1bf7b,0x3f62be48,0xbe95bf0e,0x3f75bf55,
0xbf753ec4,0x3e95bf6d,0xbf623f6d,0xbef1bec4,0xbdc93f55,0xbf7f3f0e,0x3f223e48,0xbf463f7b,0xbf353f80,0xbf358000,0xbf353f80,0xbf358000,
0x3f350000,0xbf353f80,0x3f350000,0xbf353f80,0x3f35bf80,0x3f358000,0x3f35bf80,0x3f358000,0xbf350000,0x3f35bf80,0xbf350000,0x3f35bf80,
0xbf220000,0x3f46bf80,0x3dc9bf35,0x3f7fbf35,0xbf623f7b,0xbef1be48,0xbf753f0e,0x3e95bf55,0x3e953ec4,0xbf753f6d,0xbef13f6d,0xbf623ec4,
0x3f7fbf55,0x3dc93f0e,0x3f46be48,0xbf223f7b,0x3f55bf80,0x3f0e8000,0x3f0e0000,0xbf553f80,0xbe48bec4,0x3f7bbf6d,0x3f7bbf6d,0x3e483ec4,
0xbf7b3f35,0x3e48bf35,0x3e48bf35,0x3f7bbf35,0xbf0e3f6d,0xbf553ec4,0xbf553ec4,0x3f0ebf6d,0x3ef10000,0xbf623f80,0xbf753f35,0x3e95bf35,
0x3f7fbf55,0xbdc93f0e,0xbf463f7b,0xbf223e48,0x3f22bf6d,0x3f46bec4,0x3dc93ec4,0xbf7f3f6d,0xbe95be48,0x3f75bf7b,0x3f62bf0e,0xbef13f55,
0xbf6d3f80,0xbec48000,0x3f6dbf80,0x3ec48000,0xbec43f35,0xbf6d3f35,0x3ec4bf35,0x3f6dbf35,0x3ec40000,0xbf6d3f80,0xbec40000,0x3f6dbf80,
0x3f6dbf35,0xbec43f35,0xbf6d3f35,0x3ec4bf35,0xbe950000,0x3f75bf80,0xbef13f35,0xbf623f35,0xbf463f0e,0x3f22bf55,0x3dc93e48,0xbf7f3f7b,
0xbf7f3f6d,0x3dc9bec4,0x3f22bec4,0xbf463f6d,0xbf623f7b,0xbef13e48,0x3f75bf55,0xbe953f0e,0x3f7bbf80,0x3e488000,0xbe480000,0x3f7bbf80,
0x3f55bf6d,0x3f0ebec4,0xbf0e3ec4,0x3f55bf6d,0x3f0ebf35,0x3f55bf35,0xbf553f35,0x3f0ebf35,0x3e48bec4,0x3f7bbf6d,0xbf7b3f6d,0x3e48bec4,
0x3dc90000,0xbf7f3f80,0x3f46bf35,0xbf223f35,0x3e95be48,0xbf753f7b,0x3f62bf55,0xbef13f0e,0x3ef1bec4,0xbf623f6d,0x3f75bf6d,0xbe953ec4,
0x3f22bf0e,0xbf463f55,0x3f7fbf7b,0xbdc93e48,0x3f803f80,0xbf803f80,0x3f803f80,0xbf803f80,0x3f803f80,0xbf803f80,0x3f803f80,0xbf803f80,
0x3f803f80,0xbf803f80,0x3f803f80,0xbf803f80,0x3f803f80,0xbf803f80,0x3f803f80,0xbf803f80,0xbf7fbf80,0x3dc98000,0xbf22bf35,0x3f463f35,
0xbf75bf7b,0x3e953e48,0xbef1bf0e,0x3f623f55,0xbf62bf6d,0x3ef13ec4,0xbe95bec4,0x3f753f6d,0xbf46bf55,0x3f223f0e,0xbdc9be48,0x3f7f3f7b,
0x3f7b3f80,0xbe488000,0xbe480000,0xbf7bbf80,0x3f553f6d,0xbf0ebec4,0xbf0ebec4,0xbf55bf6d,0x3f0e3f35,0xbf55bf35,0xbf55bf35,0xbf0ebf35,
0x3e483ec4,0xbf7bbf6d,0xbf7bbf6d,0xbe48bec4,0xbf75bf80,0x3e958000,0x3f623f35,0x3ef13f35,0xbf22bf55,0x3f463f0e,0x3f7f3f7b,0xbdc93e48,
0xbdc9bec4,0x3f7f3f6d,0x3f463f6d,0xbf22bec4,0x3ef13e48,0x3f623f7b,0x3e953f0e,0xbf75bf55,0x3f6d3f80,0xbec48000,0xbf6dbf80,0x3ec48000,
0x3ec43f35,0xbf6dbf35,0xbec4bf35,0x3f6d3f35,0xbec40000,0xbf6dbf80,0x3ec40000,0x3f6d3f80,0xbf6dbf35,0xbec4bf35,0x3f6d3f35,0x3ec43f35,
0xbf62bf80,0x3ef18000,0x3e953f35,0xbf75bf35,0xbdc9bf0e,0x3f7f3f55,0xbf22be48,0xbf46bf7b,0x3f463ec4,0x3f223f6d,0xbf7fbf6d,0x3dc9bec4,
0x3f753f7b,0xbe953e48,0xbef1bf55,0x3f623f0e,0x3f553f80,0xbf0e8000,0x3f0e0000,0x3f553f80,0xbe483ec4,0xbf7bbf6d,0x3f7b3f6d,0xbe483ec4,
0xbf7bbf35,0xbe48bf35,0x3e483f35,0xbf7bbf35,0xbf0ebf6d,0x3f553ec4,0xbf55bec4,0xbf0ebf6d,0xbf46bf80,0x3f228000,0xbf7fbf35,0xbdc9bf35,
0x3ef1be48,0x3f623f7b,0xbe95bf55,0x3f753f0e,0x3f753f6d,0xbe953ec4,0x3f623ec4,0x3ef13f6d,0xbdc93f0e,0xbf7fbf55,0x3f223f7b,0xbf46be48,
0x3f353f80,0xbf358000,0x3f353f80,0xbf358000,0xbf350000,0xbf35bf80,0xbf350000,0xbf35bf80,0xbf35bf80,0x3f358000,0xbf35bf80,0x3f358000,
0x3f350000,0x3f353f80,0x3f350000,0x3f353f80,0xbf22bf80,0x3f468000,0x3dc9bf35,0x3f7f3f35,0x3f623e48,0x3ef13f7b,0x3f753f55,0xbe953f0e,
0x3e953f6d,0xbf75bec4,0xbef13ec4,0xbf62bf6d,0xbf7fbf0e,0xbdc9bf55,0xbf46bf7b,0x3f22be48,0x3f0e3f80,0xbf558000,0xbf550000,0xbf0ebf80,
0xbf7bbec4,0xbe48bf6d,0xbe48bf6d,0x3f7b3ec4,0x3e48bf35,0x3f7b3f35,0x3f7b3f35,0xbe483f35,0x3f553f6d,0xbf0e3ec4,0xbf0e3ec4,0xbf55bf6d,
0xbef1bf80,0x3f628000,0x3f753f35,0xbe953f35,0x3f7f3f0e,0xbdc93f55,0xbf463e48,0xbf22bf7b,0xbf223ec4,0xbf46bf6d,0xbdc9bf6d,0x3f7f3ec4,
0xbe95bf7b,0x3f753e48,0x3f623f55,0xbef13f0e,0x3ec43f80,0xbf6d8000,0xbec4bf80,0x3f6d8000,0xbf6dbf35,0x3ec4bf35,0x3f6d3f35,0xbec43f35,
0x3f6d0000,0x3ec43f80,0xbf6d0000,0xbec4bf80,0xbec43f35,0xbf6dbf35,0x3ec4bf35,0x3f6d3f35,0xbe95bf80,0x3f758000,0xbef13f35,0xbf62bf35,
0x3f463f55,0xbf223f0e,0xbdc9bf7b,0x3f7f3e48,0xbf7fbec4,0x3dc9bf6d,0x3f223f6d,0xbf463ec4,0x3f62be48,0x3ef13f7b,0xbf75bf0e,0x3e95bf55,
0x3e483f80,0xbf7b8000,0x3f7b0000,0x3e483f80,0xbf0ebf6d,0x3f55bec4,0xbf553ec4,0xbf0ebf6d,0x3f553f35,0xbf0e3f35,0x3f0ebf35,0x3f553f35,
0xbf7bbec4,0x3e48bf6d,0xbe483f6d,0xbf7bbec4,0xbdc9bf80,0x3f7f8000,0xbf46bf35,0x3f22bf35,0x3e953f7b,0xbf753e48,0x3f623f0e,0xbef13f55,
0xbef1bf6d,0x3f62bec4,0xbf75bec4,0x3e95bf6d,0x3f223f55,0xbf463f0e,0x3f7f3e48,0xbdc93f7b,0x3f80,0xbf808000,0x3f80,0xbf808000,
0xbf80,0x3f808000,0xbf80,0x3f808000,0x3f80,0xbf808000,0x3f80,0xbf808000,0xbf80,0x3f808000,0xbf80,0x3f808000,
0x3dc9bf80,0x3f7f8000,0x3f46bf35,0x3f223f35,0xbe953f7b,0xbf75be48,0xbf623f0e,0xbef1bf55,0x3ef1bf6d,0x3f623ec4,0x3f75bec4,0x3e953f6d,
0xbf223f55,0xbf46bf0e,0xbf7f3e48,0xbdc9bf7b,0xbe483f80,0xbf7b8000,0xbf7b0000,0x3e48bf80,0x3f0ebf6d,0x3f553ec4,0x3f553ec4,0xbf0e3f6d,
0xbf553f35,0xbf0ebf35,0xbf0ebf35,0x3f55bf35,0x3f7bbec4,0x3e483f6d,0x3e483f6d,0xbf7b3ec4,0x3e95bf80,0x3f758000,0x3ef13f35,0xbf623f35,
0xbf463f55,0xbf22bf0e,0x3dc9bf7b,0x3f7fbe48,0x3f7fbec4,0x3dc93f6d,0xbf223f6d,0xbf46bec4,0xbf62be48,0x3ef1bf7b,0x3f75bf0e,0x3e953f55,
0xbec43f80,0xbf6d8000,0x3ec4bf80,0x3f6d8000,0x3f6dbf35,0x3ec43f35,0xbf6d3f35,0xbec4bf35,0xbf6d0000,0x3ec4bf80,0x3f6d0000,0xbec43f80,
0x3ec43f35,0xbf6d3f35,0xbec4bf35,0x3f6dbf35,0x3ef1bf80,0x3f628000,0xbf753f35,0xbe95bf35,0xbf7f3f0e,0xbdc9bf55,0x3f463e48,0xbf223f7b,
0x3f223ec4,0xbf463f6d,0x3dc9bf6d,0x3f7fbec4,0x3e95bf7b,0x3f75be48,0xbf623f55,0xbef1bf0e,0xbf0e3f80,0xbf558000,0x3f550000,0xbf0e3f80,
0x3f7bbec4,0xbe483f6d,0x3e48bf6d,0x3f7bbec4,0xbe48bf35,0x3f7bbf35,0xbf7b3f35,0xbe48bf35,0xbf553f6d,0xbf0ebec4,0x3f0e3ec4,0xbf553f6d,
0x3f22bf80,0x3f468000,0xbdc9bf35,0x3f7fbf35,0xbf623e48,0x3ef1bf7b,0xbf753f55,0xbe95bf0e,0xbe953f6d,0xbf753ec4,0x3ef13ec4,0xbf623f6d,
0x3f7fbf0e,0xbdc93f55,0x3f46bf7b,0x3f223e48,0xbf353f80,0xbf358000,0xbf353f80,0xbf358000,0x3f350000,0xbf353f80,0x3f350000,0xbf353f80,
0x3f35bf80,0x3f358000,0x3f35bf80,0x3f358000,0xbf350000,0x3f35bf80,0xbf350000,0x3f35bf80,0x3f46bf80,0x3f228000,0x3f7fbf35,0xbdc93f35,
0xbef1be48,0x3f62bf7b,0x3e95bf55,0x3f75bf0e,0xbf753f6d,0xbe95bec4,0xbf623ec4,0x3ef1bf6d,0x3dc93f0e,0xbf7f3f55,0xbf223f7b,0xbf463e48,
0xbf553f80,0xbf0e8000,0xbf0e0000,0x3f55bf80,0x3e483ec4,0xbf7b3f6d,0xbf7b3f6d,0xbe48bec4,0x3f7bbf35,0xbe483f35,0xbe483f35,0xbf7b3f35,
0x3f0ebf6d,0x3f55bec4,0x3f55bec4,0xbf0e3f6d,0x3f62bf80,0x3ef18000,0xbe953f35,0xbf753f35,0x3dc9bf0e,0x3f7fbf55,0x3f22be48,0xbf463f7b,
0xbf463ec4,0x3f22bf6d,0x3f7fbf6d,0x3dc93ec4,0xbf753f7b,0xbe95be48,0x3ef1bf55,0x3f62bf0e,0xbf6d3f80,0xbec48000,0x3f6dbf80,0x3ec48000,
0xbec43f35,0xbf6d3f35,0x3ec4bf35,0x3f6dbf35,0x3ec40000,0xbf6d3f80,0xbec40000,0x3f6dbf80,0x3f6dbf35,0xbec43f35,0xbf6d3f35,0x3ec4bf35,
0x3f75bf80,0x3e958000,0xbf623f35,0x3ef1bf35,0x3f22bf55,0x3f46bf0e,0xbf7f3f7b,0xbdc9be48,0x3dc9bec4,0x3f7fbf6d,0xbf463f6d,0xbf223ec4,
0xbef13e48,0x3f62bf7b,0xbe953f0e,0xbf753f55,0xbf7b3f80,0xbe488000,0x3e480000,0xbf7b3f80,0xbf553f6d,0xbf0e3ec4,0x3f0ebec4,0xbf553f6d,
0xbf0e3f35,0xbf553f35,0x3f55bf35,0xbf0e3f35,0xbe483ec4,0xbf7b3f6d,0x3f7bbf6d,0xbe483ec4,0x3f7fbf80,0x3dc98000,0x3f22bf35,0x3f46bf35,
0x3f75bf7b,0x3e95be48,0x3ef1bf0e,0x3f62bf55,0x3f62bf6d,0x3ef1bec4,0x3e95bec4,0x3f75bf6d,0x3f46bf55,0x3f22bf0e,0x3dc9be48,0x3f7fbf7b,
0x3f803f80,0xbf803f80,0x3f803f80,0xbf803f80,0x3f803f80,0xbf803f80,0x3f803f80,0xbf803f80,0x3f803f80,0xbf803f80,0x3f803f80,0xbf803f80,
0x3f803f80,0xbf803f80,0x3f803f80,0xbf803f80,0x3dc90000,0x3f7f3f80,0x3f463f35,0x3f223f35,0x3e953e48,0x3f753f7b,0x3f623f55,0x3ef13f0e,
0x3ef13ec4,0x3f623f6d,0x3f753f6d,0x3e953ec4,0x3f223f0e,0x3f463f55,0x3f7f3f7b,0x3dc93e48,0xbf7bbf80,0x3e488000,0x3e480000,0x3f7b3f80,
0xbf55bf6d,0x3f0e3ec4,0x3f0e3ec4,0x3f553f6d,0xbf0ebf35,0x3f553f35,0x3f553f35,0x3f0e3f35,0xbe48bec4,0x3f7b3f6d,0x3f7b3f6d,0x3e483ec4,
0xbe950000,0xbf75bf80,0xbef1bf35,0x3f623f35,0xbf46bf0e,0xbf22bf55,0x3dc9be48,0x3f7f3f7b,0xbf7fbf6d,0xbdc9bec4,0x3f223ec4,0x3f463f6d,
0xbf62bf7b,0x3ef13e48,0x3f753f55,0x3e953f0e,0x3f6d3f80,0xbec48000,0xbf6dbf80,0x3ec48000,0x3ec43f35,0xbf6dbf35,0xbec4bf35,0x3f6d3f35,
0xbec40000,0xbf6dbf80,0x3ec40000,0x3f6d3f80,0xbf6dbf35,0xbec4bf35,0x3f6d3f35,0x3ec43f35,0x3ef10000,0x3f623f80,0xbf75bf35,0xbe95bf35,
0x3f7f3f55,0x3dc93f0e,0xbf46bf7b,0x3f223e48,0x3f223f6d,0xbf46bec4,0x3dc9bec4,0x3f7f3f6d,0xbe953e48,0xbf75bf7b,0x3f623f0e,0x3ef13f55,
0xbf55bf80,0x3f0e8000,0xbf0e0000,0xbf55bf80,0x3e48bec4,0x3f7b3f6d,0xbf7bbf6d,0x3e48bec4,0x3f7b3f35,0x3e483f35,0xbe48bf35,0x3f7b3f35,
0x3f0e3f6d,0xbf55bec4,0x3f553ec4,0x3f0e3f6d,0xbf220000,0xbf46bf80,0x3dc93f35,0xbf7fbf35,0xbf62bf7b,0x3ef1be48,0xbf75bf0e,0xbe95bf55,
0x3e95bec4,0x3f753f6d,0xbef1bf6d,0x3f623ec4,0x3f7f3f55,0xbdc93f0e,0x3f463e48,0x3f223f7b,0x3f353f80,0xbf358000,0x3f353f80,0xbf358000,
0xbf350000,0xbf35bf80,0xbf350000,0xbf35bf80,0xbf35bf80,0x3f358000,0xbf35bf80,0x3f358000,0x3f350000,0x3f353f80,0x3f350000,0x3f353f80,
0x3f460000,0x3f223f80,0x3f7f3f35,0xbdc93f35,0x3ef13f7b,0xbf62be48,0xbe953f0e,0xbf75bf55,0xbf75bec4,0xbe95bf6d,0xbf62bf6d,0x3ef1bec4,
0xbdc9bf55,0x3f7f3f0e,0x3f22be48,0x3f463f7b,0xbf0ebf80,0x3f558000,0x3f550000,0x3f0e3f80,0x3f7b3ec4,0x3e483f6d,0x3e483f6d,0xbf7bbec4,
0xbe483f35,0xbf7bbf35,0xbf7bbf35,0x3e48bf35,0xbf55bf6d,0x3f0ebec4,0x3f0ebec4,0x3f553f6d,0xbf620000,0xbef1bf80,0x3e95bf35,0x3f753f35,
0x3dc9bf55,0x3f7f3f0e,0x3f223f7b,0xbf463e48,0x3f463f6d,0xbf223ec4,0xbf7fbec4,0xbdc9bf6d,0xbf75be48,0xbe95bf7b,0x3ef1bf0e,0x3f623f55,
0x3ec43f80,0xbf6d8000,0xbec4bf80,0x3f6d8000,0xbf6dbf35,0x3ec4bf35,0x3f6d3f35,0xbec43f35,0x3f6d0000,0x3ec43f80,0xbf6d0000,0xbec4bf80,
0xbec43f35,0xbf6dbf35,0x3ec4bf35,0x3f6d3f35,0x3f750000,0x3e953f80,0xbf62bf35,0x3ef1bf35,0xbf223f0e,0xbf46bf55,0x3f7f3e48,0x3dc93f7b,
0x3dc9bf6d,0x3f7f3ec4,0xbf463ec4,0xbf22bf6d,0x3ef13f7b,0xbf623e48,0x3e95bf55,0x3f753f0e,0xbe48bf80,0x3f7b8000,0xbf7b0000,0xbe48bf80,
0x3f0e3f6d,0xbf553ec4,0x3f55bec4,0x3f0e3f6d,0xbf55bf35,0x3f0ebf35,0xbf0e3f35,0xbf55bf35,0x3f7b3ec4,0xbe483f6d,0x3e48bf6d,0x3f7b3ec4,
0xbf7f0000,0xbdc9bf80,0xbf223f35,0xbf46bf35,0x3f75be48,0x3e953f7b,0x3ef1bf55,0x3f623f0e,0xbf623ec4,0xbef1bf6d,0xbe953f6d,0xbf75bec4,
0x3f46bf0e,0x3f223f55,0x3dc9bf7b,0x3f7f3e48,0x3f80,0xbf808000,0x3f80,0xbf808000,0xbf80,0x3f808000,0xbf80,0x3f808000,
0x3f80,0xbf808000,0x3f80,0xbf808000,0xbf80,0x3f808000,0xbf80,0x3f808000,0x3f7f0000,0xbdc93f80,0x3f223f35,0xbf463f35,
0xbf75be48,0x3e95bf7b,0xbef1bf55,0x3f62bf0e,0x3f623ec4,0xbef13f6d,0x3e953f6d,0xbf753ec4,0xbf46bf0e,0x3f22bf55,0xbdc9bf7b,0x3f7fbe48,
0x3e48bf80,0x3f7b8000,0x3f7b0000,0xbe483f80,0xbf0e3f6d,0xbf55bec4,0xbf55bec4,0x3f0ebf6d,0x3f55bf35,0x3f0e3f35,0x3f0e3f35,0xbf553f35,
0xbf7b3ec4,0xbe48bf6d,0xbe48bf6d,0x3f7bbec4,0xbf750000,0x3e95bf80,0x3f62bf35,0x3ef13f35,0x3f223f0e,0xbf463f55,0xbf7f3e48,0x3dc9bf7b,
0xbdc9bf6d,0x3f7fbec4,0x3f463ec4,0xbf223f6d,0xbef13f7b,0xbf62be48,0xbe95bf55,0x3f75bf0e,0xbec43f80,0xbf6d8000,0x3ec4bf80,0x3f6d8000,
0x3f6dbf35,0x3ec43f35,0xbf6d3f35,0xbec4bf35,0xbf6d0000,0x3ec4bf80,0x3f6d0000,0xbec43f80,0x3ec43f35,0xbf6d3f35,0xbec4bf35,0x3f6dbf35,
0x3f620000,0xbef13f80,0xbe95bf35,0x3f75bf35,0xbdc9bf55,0x3f7fbf0e,0xbf223f7b,0xbf46be48,0xbf463f6d,0xbf22bec4,0x3f7fbec4,0xbdc93f6d,
0x3f75be48,0xbe953f7b,0xbef1bf0e,0x3f62bf55,0x3f0ebf80,0x3f558000,0xbf550000,0x3f0ebf80,0xbf7b3ec4,0x3e48bf6d,0xbe483f6d,0xbf7b3ec4,
0x3e483f35,0xbf7b3f35,0x3f7bbf35,0x3e483f35,0x3f55bf6d,0x3f0e3ec4,0xbf0ebec4,0x3f55bf6d,0xbf460000,0x3f22bf80,0xbf7f3f35,0xbdc9bf35,
0xbef13f7b,0xbf623e48,0x3e953f0e,0xbf753f55,0x3f75bec4,0xbe953f6d,0x3f62bf6d,0x3ef13ec4,0x3dc9bf55,0x3f7fbf0e,0xbf22be48,0x3f46bf7b,
0xbf353f80,0xbf358000,0xbf353f80,0xbf358000,0x3f350000,0xbf353f80,0x3f350000,0xbf353f80,0x3f35bf80,0x3f358000,0x3f35bf80,0x3f358000,
0xbf350000,0x3f35bf80,0xbf350000,0x3f35bf80,0x3f220000,0xbf463f80,0xbdc93f35,0xbf7f3f35,0x3f62bf7b,0x3ef13e48,0x3f75bf0e,0xbe953f55,
0xbe95bec4,0x3f75bf6d,0x3ef1bf6d,0x3f62bec4,0xbf7f3f55,0xbdc9bf0e,0xbf463e48,0x3f22bf7b,0x3f55bf80,0x3f0e8000,0x3f0e0000,0xbf553f80,
0xbe48bec4,0x3f7bbf6d,0x3f7bbf6d,0x3e483ec4,0xbf7b3f35,0x3e48bf35,0x3e48bf35,0x3f7bbf35,0xbf0e3f6d,0xbf553ec4,0xbf553ec4,0x3f0ebf6d,
0xbef10000,0x3f62bf80,0x3f75bf35,0xbe953f35,0xbf7f3f55,0x3dc9bf0e,0x3f46bf7b,0x3f22be48,0xbf223f6d,0xbf463ec4,0xbdc9bec4,0x3f7fbf6d,
0x3e953e48,0xbf753f7b,0xbf623f0e,0x3ef1bf55,0xbf6d3f80,0xbec48000,0x3f6dbf80,0x3ec48000,0xbec43f35,0xbf6d3f35,0x3ec4bf35,0x3f6dbf35,
0x3ec40000,0xbf6d3f80,0xbec40000,0x3f6dbf80,0x3f6dbf35,0xbec43f35,0xbf6d3f35,0x3ec4bf35,0x3e950000,0xbf753f80,0x3ef1bf35,0x3f62bf35,
0x3f46bf0e,0xbf223f55,0xbdc9be48,0x3f7fbf7b,0x3f7fbf6d,0xbdc93ec4,0xbf223ec4,0x3f46bf6d,0x3f62bf7b,0x3ef1be48,0xbf753f55,0x3e95bf0e,
0x3f7bbf80,0x3e488000,0xbe480000,0x3f7bbf80,0x3f55bf6d,0x3f0ebec4,0xbf0e3ec4,0x3f55bf6d,0x3f0ebf35,0x3f55bf35,0xbf553f35,0x3f0ebf35,
0x3e48bec4,0x3f7bbf6d,0xbf7b3f6d,0x3e48bec4,0xbdc90000,0x3f7fbf80,0xbf463f35,0x3f22bf35,0xbe953e48,0x3f75bf7b,0xbf623f55,0x3ef1bf0e,
0xbef13ec4,0x3f62bf6d,0xbf753f6d,0x3e95bec4,0xbf223f0e,0x3f46bf55,0xbf7f3f7b,0x3dc9be48,0x3f803f80,0xbf353f35,0x3f803f80,0xbf353f35,
0x3f803f80,0xbf353f35,0x3f803f80,0xbf353f35,0x3f803f80,0xbf353f35,0x3f803f80,0xbf353f35,0x3f803f80,0xbf353f35,0x3f803f80,0xbf353f35,
0x3f7e3f80,0xbdfbbcc9,0x3f1d3f31,0xbf4abf39,0x3f733f7a,0xbea1be60,0x3ee63f09,0xbf65bf58,0x3f5f3f6a,0xbefcbecf,0x3e893eb8,0xbf77bf6f,
0x3f423f51,0xbf27bf13,0x3d973e2f,0xbf7fbf7c,0x3f783f80,0xbe79bd49,0xbe79bd49,0xbf78bf80,0x3f4e3f67,0xbf18bedb,0xbf18bedb,0xbf4ebf67,
0x3f043f2c,0xbf5cbf3e,0xbf5cbf3e,0xbf04bf2c,0x3e163eac,0xbf7dbf71,0xbf7dbf71,0xbe16beac,0x3f6f3f7f,0xbeb8bd97,0xbf6abf42,0xbecfbf27,
0x3f133f4a,0xbf51bf1d,0xbf7cbf7e,0x3e2fbdfb,0x3cc93ea1,0xbf80bf73,0xbf39bf65,0x3f313ee6,0xbf09be89,0xbf58bf77,0xbe60befc,0x3f7a3f5f,
0x3f623f7f,0xbef1bdc9,0xbf62bf7f,0x3ef13dc9,0x3e953f22,0xbf75bf46,0xbe95bf22,0x3f753f46,0xbef1bdc9,0xbf62bf7f,0x3ef13dc9,0x3f623f7f,
0xbf75bf46,0xbe95bf22,0x3f753f46,0x3e953f22,0x3f513f7e,0xbf13bdfb,0xbe2fbf1d,0x3f7c3f4a,0xbcc93ee6,0xbf80bf65,0x3f393ea1,0x3f313f73,
0xbf58befc,0xbf09bf5f,0x3f7a3f77,0xbe603e89,0xbf6abf7f,0x3ecfbd97,0x3eb83f42,0xbf6fbf27,0x3f3e3f7d,0xbf2cbe16,0x3f2c3e16,0x3f3e3f7d,
0xbeac3e79,0xbf71bf78,0x3f713f78,0xbeac3e79,0xbf80bf4e,0xbd49bf18,0x3d493f18,0xbf80bf4e,0xbedbbf5c,0x3f673f04,0xbf67bf04,0xbedbbf5c,
0x3f273f7c,0xbf42be2f,0x3f7f3f51,0xbd973f13,0xbf1d3cc9,0xbf4abf80,0x3dfb3f39,0xbf7ebf31,0xbf65bf7a,0x3ee6be60,0xbf73bf09,0xbea1bf58,
0x3e89becf,0x3f773f6a,0xbefcbf6f,0x3f5f3eb8,0x3f0e3f7b,0xbf55be48,0x3f0e3f7b,0xbf55be48,0xbf55be48,0xbf0ebf7b,0xbf55be48,0xbf0ebf7b,
0xbf0ebf7b,0x3f553e48,0xbf0ebf7b,0x3f553e48,0x3f553e48,0x3f0e3f7b,0x3f553e48,0x3f0e3f7b,0x3ee63f7a,0xbf65be60,0xbea13f09,0xbf73bf58,
0xbf77becf,0xbe89bf6a,0xbf5fbf6f,0x3efcbeb8,0xbd97bf51,0x3f7f3f13,0x3f27be2f,0x3f423f7c,0x3f7e3f39,0xbdfb3f31,0x3f1d3f80,0xbf4abcc9,
0x3eac3f78,0xbf71be79,0xbf71be79,0xbeacbf78,0xbf80bf18,0x3d49bf4e,0x3d49bf4e,0x3f803f18,0x3edbbf04,0x3f673f5c,0x3f673f5c,0xbedb3f04,
0x3f2c3f7d,0xbf3e3e16,0xbf3e3e16,0xbf2cbf7d,0x3e603f77,0xbf7abe89,0xbf58bf5f,0x3f09befc,0xbf6fbf42,0x3eb8bf27,0x3f6a3d97,0x3ecf3f7f,
0x3f51bdfb,0x3f133f7e,0xbe2f3f4a,0xbf7cbf1d,0x3cc93f65,0xbf80bee6,0xbf39bf73,0x3f31bea1,0x3dc93f75,0xbf7fbe95,0xbdc9bf75,0x3f7f3e95,
0xbf46bf62,0x3f22bef1,0x3f463f62,0xbf223ef1,0x3f7f3e95,0x3dc93f75,0xbf7fbe95,0xbdc9bf75,0xbf223ef1,0xbf46bf62,0x3f22bef1,0x3f463f62,
0xbcc93f73,0xbf80bea1,0x3f39bee6,0x3f313f65,0xbf09bf77,0x3f58be89,0xbe603f5f,0xbf7abefc,0x3f6a3f27,0xbecf3f42,0xbeb8bf7f,0x3f6fbd97,
0xbf7cbdfb,0xbe2fbf7e,0x3f513f4a,0xbf133f1d,0xbe163f71,0xbf7dbeac,0x3f7d3eac,0xbe163f71,0xbe79bf80,0x3f78bd49,0xbf783d49,0xbe79bf80,
0x3f183f67,0xbf4e3edb,0x3f4ebedb,0x3f183f67,0xbf5cbf2c,0x3f04bf3e,0xbf043f3e,0xbf5cbf2c,0xbe893f6f,0xbf77beb8,0x3efc3f6a,0xbf5f3ecf,
0x3d97bf7c,0x3f7f3e2f,0xbf27bf51,0x3f42bf13,0x3dfb3f80,0xbf7e3cc9,0x3f4a3f31,0xbf1d3f39,0xbea1bf7a,0x3f73be60,0xbf65bf09,0x3ee6bf58,
0xbec43f6d,0xbf6dbec4,0xbec43f6d,0xbf6dbec4,0x3ec4bf6d,0x3f6d3ec4,0x3ec4bf6d,0x3f6d3ec4,0xbec43f6d,0xbf6dbec4,0xbec43f6d,0xbf6dbec4,
0x3ec4bf6d,0x3f6d3ec4,0x3ec4bf6d,0x3f6d3ec4,0xbefc3f6a,0xbf5fbecf,0xbf773eb8,0xbe89bf6f,0x3f27bf51,0x3f423f13,0x3f7fbe2f,0x3d973f7c,
0xbf4a3f31,0xbf1dbf39,0xbf7ebcc9,0x3dfbbf80,0x3f65bf09,0x3ee63f58,0x3f733e60,0xbea13f7a,0xbf183f67,0xbf4ebedb,0xbf4ebedb,0x3f18bf67,
0x3f5cbf2c,0x3f043f3e,0x3f043f3e,0xbf5c3f2c,0xbf7d3eac,0xbe16bf71,0xbe16bf71,0x3f7dbeac,0x3f783d49,0xbe793f80,0xbe793f80,0xbf78bd49,
0xbf313f65,0xbf39bee6,0xbcc9bf73,0x3f80bea1,0x3f7abefc,0x3e603f5f,0xbf093f77,0xbf58be89,0xbf6fbd97,0x3eb8bf7f,0x3f6abf27,0x3ecf3f42,
0x3f133f1d,0xbf513f4a,0xbf7c3dfb,0x3e2fbf7e,0xbf463f62,0xbf22bef1,0x3f46bf62,0x3f223ef1,0x3f7fbe95,0xbdc93f75,0xbf7f3e95,0x3dc9bf75,
0xbf22bef1,0x3f46bf62,0x3f223ef1,0xbf463f62,0xbdc93f75,0xbf7f3e95,0x3dc9bf75,0x3f7fbe95,0xbf583f5f,0xbf09befc,0x3f7abe89,0xbe603f77,
0x3f6abd97,0xbecf3f7f,0xbeb8bf27,0x3f6fbf42,0xbe2fbf4a,0x3f7cbf1d,0xbf133f7e,0xbf51bdfb,0xbf393f73,0xbf31bea1,0x3f80bee6,0xbcc93f65,
0xbf673f5c,0xbedbbf04,0x3edb3f04,0xbf673f5c,0x3f3e3e16,0xbf2c3f7d,0x3f2cbf7d,0x3f3e3e16,0x3eacbf78,0x3f71be79,0xbf713e79,0x3eacbf78,
0xbf803f18,0xbd49bf4e,0x3d493f4e,0xbf803f18,0xbf733f58,0xbea1bf09,0xbee63f7a,0xbf653e60,0x3efc3eb8,0xbf5f3f6f,0x3f77becf,0xbe893f6a,
0x3f42bf7c,0x3f273e2f,0x3d97bf51,0x3f7fbf13,0xbf4a3cc9,0x3f1dbf80,0xbf7e3f39,0xbdfbbf31,0xbf7b3f55,0xbe48bf0e,0xbf7b3f55,0xbe48bf0e,
0x3e483f0e,0xbf7b3f55,0x3e483f0e,0xbf7b3f55,0x3f7bbf55,0x3e483f0e,0x3f7bbf55,0x3e483f0e,0xbe48bf0e,0x3f7bbf55,0xbe48bf0e,0x3f7bbf55,
0xbf7f3f51,0xbd97bf13,0xbf423e2f,0x3f27bf7c,0xbdfb3f39,0xbf7e3f31,0xbf4a3f80,0xbf1dbcc9,0x3f73bf09,0xbea13f58,0x3ee63e60,0xbf653f7a,
0x3efcbf6f,0x3f5fbeb8,0x3f77bf6a,0x3e893ecf,0xbf803f4e,0x3d49bf18,0x3d49bf18,0x3f80bf4e,0xbedb3f5c,0xbf673f04,0xbf673f04,0x3edbbf5c,
0x3f2cbe16,0xbf3e3f7d,0xbf3e3f7d,0xbf2c3e16,0x3f71bf78,0x3eac3e79,0x3eac3e79,0xbf713f78,0xbf7c3f4a,0x3e2fbf1d,0x3f51bf7e,0x3f13bdfb,
0xbf313f73,0xbf393ea1,0xbcc9bee6,0x3f80bf65,0x3e603e89,0xbf7a3f77,0xbf583efc,0x3f09bf5f,0x3f6fbf27,0xbeb83f42,0xbf6a3f7f,0xbecfbd97,
0xbf753f46,0x3e95bf22,0x3f75bf46,0xbe953f22,0xbf623f7f,0xbef13dc9,0x3f62bf7f,0x3ef1bdc9,0xbe953f22,0xbf753f46,0x3e95bf22,0x3f75bf46,
0x3ef1bdc9,0xbf623f7f,0xbef13dc9,0x3f62bf7f,0xbf6a3f42,0x3ecfbf27,0x3eb8bd97,0xbf6f3f7f,0xbf7c3f7e,0xbe2fbdfb,0x3f51bf1d,0xbf133f4a,
0xbf393f65,0xbf313ee6,0x3f80bf73,0xbcc93ea1,0xbe603efc,0xbf7a3f5f,0x3f58bf77,0x3f09be89,0xbf5c3f3e,0x3f04bf2c,0xbf043f2c,0xbf5c3f3e,
0xbf7d3f71,0x3e16beac,0xbe163eac,0xbf7d3f71,0xbf783f80,0xbe793d49,0x3e79bd49,0xbf783f80,0xbf4e3f67,0xbf183edb,0x3f18bedb,0xbf4e3f67,
0xbf4a3f39,0x3f1dbf31,0xbf7e3f80,0xbdfb3cc9,0xbf653f58,0x3ee6bf09,0xbf733f7a,0xbea13e60,0xbf773f6f,0x3e89beb8,0xbf5f3f6a,0xbefc3ecf,
0xbf7f3f7c,0x3d97be2f,0xbf423f51,0xbf273f13,0x3f803f80,0xbf353f35,0x3f803f80,0xbf353f35,0x3f803f80,0xbf353f35,0x3f803f80,0xbf353f35,
0x3f803f80,0xbf353f35,0x3f803f80,0xbf353f35,0x3f803f80,0xbf353f35,0x3f803f80,0xbf353f35,0xbdfbbcc9,0xbf7ebf80,0xbf4abf39,0xbf1dbf31,
0xbea1be60,0xbf73bf7a,0xbf65bf58,0xbee6bf09,0xbefcbecf,0xbf5fbf6a,0xbf77bf6f,0xbe89beb8,0xbf27bf13,0xbf42bf51,0xbf7fbf7c,0xbd97be2f,
0xbf78bf80,0x3e793d49,0x3e793d49,0x3f783f80,0xbf4ebf67,0x3f183edb,0x3f183edb,0x3f4e3f67,0xbf04bf2c,0x3f5c3f3e,0x3f5c3f3e,0x3f043f2c,
0xbe16beac,0x3f7d3f71,0x3f7d3f71,0x3e163eac,0x3eb83d97,0x3f6f3f7f,0x3ecf3f27,0xbf6abf42,0x3f513f1d,0x3f133f4a,0xbe2f3dfb,0xbf7cbf7e,
0x3f803f73,0x3cc93ea1,0xbf31bee6,0xbf39bf65,0x3f583f77,0xbf09be89,0xbf7abf5f,0xbe60befc,0x3f623f7f,0xbef1bdc9,0xbf62bf7f,0x3ef13dc9,
0x3e953f22,0xbf75bf46,0xbe95bf22,0x3f753f46,0xbef1bdc9,0xbf62bf7f,0x3ef13dc9,0x3f623f7f,0xbf75bf46,0xbe95bf22,0x3f753f46,0x3e953f22,
0xbf13bdfb,0xbf51bf7e,0x3f7c3f4a,0x3e2f3f1d,0xbf80bf65,0x3cc9bee6,0x3f313f73,0xbf39bea1,0xbf09bf5f,0x3f583efc,0xbe603e89,0xbf7abf77,
0x3ecfbd97,0x3f6a3f7f,0xbf6fbf27,0xbeb8bf42,0xbf3ebf7d,0x3f2c3e16,0xbf2cbe16,0xbf3ebf7d,0x3eacbe79,0x3f713f78,0xbf71bf78,0x3eacbe79,
0x3f803f4e,0x3d493f18,0xbd49bf18,0x3f803f4e,0x3edb3f5c,0xbf67bf04,0x3f673f04,0x3edb3f5c,0x3f423e2f,0x3f273f7c,0x3d97bf13,0x3f7f3f51,
0x3f4a3f80,0xbf1d3cc9,0x3f7e3f31,0x3dfb3f39,0xbee63e60,0xbf65bf7a,0x3ea13f58,0xbf73bf09,0xbf77bf6a,0x3e89becf,0xbf5fbeb8,0xbefcbf6f,
0x3f0e3f7b,0xbf55be48,0x3f0e3f7b,0xbf55be48,0xbf55be48,0xbf0ebf7b,0xbf55be48,0xbf0ebf7b,0xbf0ebf7b,0x3f553e48,0xbf0ebf7b,0x3f553e48,
0x3f553e48,0x3f0e3f7b,0x3f553e48,0x3f0e3f7b,0xbf65be60,0xbee6bf7a,0xbf73bf58,0x3ea1bf09,0xbe89bf6a,0x3f773ecf,0x3efcbeb8,0x3f5f3f6f,
0x3f7f3f13,0x3d973f51,0x3f423f7c,0xbf273e2f,0xbdfb3f31,0xbf7ebf39,0xbf4abcc9,0xbf1dbf80,0xbeacbf78,0x3f713e79,0x3f713e79,0x3eac3f78,
0x3f803f18,0xbd493f4e,0xbd493f4e,0xbf80bf18,0xbedb3f04,0xbf67bf5c,0xbf67bf5c,0x3edbbf04,0xbf2cbf7d,0x3f3ebe16,0x3f3ebe16,0x3f2c3f7d,
0x3f7a3e89,0x3e603f77,0xbf093efc,0xbf58bf5f,0xbeb83f27,0xbf6fbf42,0xbecfbf7f,0x3f6a3d97,0xbf13bf7e,0x3f51bdfb,0x3f7c3f1d,0xbe2f3f4a,
0x3f803ee6,0x3cc93f65,0xbf313ea1,0xbf39bf73,0x3dc93f75,0xbf7fbe95,0xbdc9bf75,0x3f7f3e95,0xbf46bf62,0x3f22bef1,0x3f463f62,0xbf223ef1,
0x3f7f3e95,0x3dc93f75,0xbf7fbe95,0xbdc9bf75,0xbf223ef1,0xbf46bf62,0x3f22bef1,0x3f463f62,0xbf80bea1,0x3cc9bf73,0x3f313f65,0xbf393ee6,
0x3f58be89,0x3f093f77,0xbf7abefc,0x3e60bf5f,0xbecf3f42,0xbf6abf27,0x3f6fbd97,0x3eb83f7f,0xbe2fbf7e,0x3f7c3dfb,0xbf133f1d,0xbf51bf4a,
0x3e16bf71,0x3f7d3eac,0xbf7dbeac,0x3e16bf71,0x3e793f80,0xbf783d49,0x3f78bd49,0x3e793f80,0xbf18bf67,0x3f4ebedb,0xbf4e3edb,0xbf18bf67,
0x3f5c3f2c,0xbf043f3e,0x3f04bf3e,0x3f5c3f2c,0x3f773eb8,0xbe893f6f,0x3f5fbecf,0x3efc3f6a,0xbf7fbe2f,0x3d97bf7c,0xbf423f13,0xbf27bf51,
0x3f7ebcc9,0x3dfb3f80,0x3f1dbf39,0x3f4a3f31,0xbf733e60,0xbea1bf7a,0xbee63f58,0xbf65bf09,0xbec43f6d,0xbf6dbec4,0xbec43f6d,0xbf6dbec4,
0x3ec4bf6d,0x3f6d3ec4,0x3ec4bf6d,0x3f6d3ec4,0xbec43f6d,0xbf6dbec4,0xbec43f6d,0xbf6dbec4,0x3ec4bf6d,0x3f6d3ec4,0x3ec4bf6d,0x3f6d3ec4,
0xbf5fbecf,0x3efcbf6a,0xbe89bf6f,0x3f77beb8,0x3f423f13,0xbf273f51,0x3d973f7c,0xbf7f3e2f,0xbf1dbf39,0x3f4abf31,0x3dfbbf80,0x3f7e3cc9,
0x3ee63f58,0xbf653f09,0xbea13f7a,0xbf73be60,0x3f18bf67,0x3f4e3edb,0x3f4e3edb,0xbf183f67,0xbf5c3f2c,0xbf04bf3e,0xbf04bf3e,0x3f5cbf2c,
0x3f7dbeac,0x3e163f71,0x3e163f71,0xbf7d3eac,0xbf78bd49,0x3e79bf80,0x3e79bf80,0x3f783d49,0x3f393ee6,0xbf313f65,0xbf803ea1,0xbcc9bf73,
0xbe60bf5f,0x3f7abefc,0x3f583e89,0xbf093f77,0xbeb83f7f,0xbf6fbd97,0xbecfbf42,0x3f6abf27,0x3f51bf4a,0x3f133f1d,0xbe2f3f7e,0xbf7c3dfb,
0xbf463f62,0xbf22bef1,0x3f46bf62,0x3f223ef1,0x3f7fbe95,0xbdc93f75,0xbf7f3e95,0x3dc9bf75,0xbf22bef1,0x3f46bf62,0x3f223ef1,0xbf463f62,
0xbdc93f75,0xbf7f3e95,0x3dc9bf75,0x3f7fbe95,0xbf09befc,0x3f58bf5f,0xbe603f77,0xbf7a3e89,0xbecf3f7f,0xbf6a3d97,0x3f6fbf42,0x3eb83f27,
0x3f7cbf1d,0x3e2f3f4a,0xbf51bdfb,0x3f13bf7e,0xbf31bea1,0x3f39bf73,0xbcc93f65,0xbf803ee6,0x3f67bf5c,0x3edb3f04,0xbedbbf04,0x3f67bf5c,
0xbf3ebe16,0x3f2cbf7d,0xbf2c3f7d,0xbf3ebe16,0xbeac3f78,0xbf713e79,0x3f71be79,0xbeac3f78,0x3f80bf18,0x3d493f4e,0xbd49bf4e,0x3f80bf18,
0x3ea13f09,0xbf733f58,0x3f65be60,0xbee63f7a,0x3f5fbf6f,0x3efc3eb8,0x3e89bf6a,0x3f77becf,0xbf27be2f,0x3f42bf7c,0xbf7f3f13,0x3d97bf51,
0xbf1d3f80,0xbf4a3cc9,0x3dfb3f31,0xbf7e3f39,0xbf7b3f55,0xbe48bf0e,0xbf7b3f55,0xbe48bf0e,0x3e483f0e,0xbf7b3f55,0x3e483f0e,0xbf7b3f55,
0x3f7bbf55,0x3e483f0e,0x3f7bbf55,0x3e483f0e,0xbe48bf0e,0x3f7bbf55,0xbe48bf0e,0x3f7bbf55,0xbd97bf13,0x3f7fbf51,0x3f27bf7c,0x3f42be2f,
0xbf7e3f31,0x3dfbbf39,0xbf1dbcc9,0x3f4abf80,0xbea13f58,0xbf733f09,0xbf653f7a,0xbee6be60,0x3f5fbeb8,0xbefc3f6f,0x3e893ecf,0xbf773f6a,
0x3f80bf4e,0xbd493f18,0xbd493f18,0xbf803f4e,0x3edbbf5c,0x3f67bf04,0x3f67bf04,0xbedb3f5c,0xbf2c3e16,0x3f3ebf7d,0x3f3ebf7d,0x3f2cbe16,
0xbf713f78,0xbeacbe79,0xbeacbe79,0x3f71bf78,0xbe2f3f1d,0xbf7c3f4a,0xbf133dfb,0x3f51bf7e,0x3f39bea1,0xbf313f73,0xbf803f65,0xbcc9bee6,
0x3f7abf77,0x3e603e89,0xbf093f5f,0xbf583efc,0x3eb8bf42,0x3f6fbf27,0x3ecf3d97,0xbf6a3f7f,0xbf753f46,0x3e95bf22,0x3f75bf46,0xbe953f22,
0xbf623f7f,0xbef13dc9,0x3f62bf7f,0x3ef1bdc9,0xbe953f22,0xbf753f46,0x3e95bf22,0x3f75bf46,0x3ef1bdc9,0xbf623f7f,0xbef13dc9,0x3f62bf7f,
0x3ecfbf27,0x3f6abf42,0xbf6f3f7f,0xbeb83d97,0xbe2fbdfb,0x3f7cbf7e,0xbf133f4a,0xbf513f1d,0xbf313ee6,0x3f39bf65,0xbcc93ea1,0xbf803f73,
0xbf7a3f5f,0x3e60befc,0x3f09be89,0xbf583f77,0x3f5cbf3e,0xbf043f2c,0x3f04bf2c,0x3f5cbf3e,0x3f7dbf71,0xbe163eac,0x3e16beac,0x3f7dbf71,
0x3f78bf80,0x3e79bd49,0xbe793d49,0x3f78bf80,0x3f4ebf67,0x3f18bedb,0xbf183edb,0x3f4ebf67,0xbf1d3f31,0xbf4a3f39,0x3dfbbcc9,0xbf7e3f80,
0xbee63f09,0xbf653f58,0x3ea1be60,0xbf733f7a,0xbe893eb8,0xbf773f6f,0x3efcbecf,0xbf5f3f6a,0xbd973e2f,0xbf7f3f7c,0x3f27bf13,0xbf423f51,
0x3f803f80,0xbf353f35,0x3f803f80,0xbf353f35,0x3f803f80,0xbf353f35,0x3f803f80,0xbf353f35,0x3f803f80,0xbf353f35,0x3f803f80,0xbf353f35,
0x3f803f80,0xbf353f35,0x3f803f80,0xbf353f35,0xbf7ebf80,0x3dfb3cc9,0xbf1dbf31,0x3f4a3f39,0xbf73bf7a,0x3ea13e60,0xbee6bf09,0x3f653f58,
0xbf5fbf6a,0x3efc3ecf,0xbe89beb8,0x3f773f6f,0xbf42bf51,0x3f273f13,0xbd97be2f,0x3f7f3f7c,0x3f783f80,0xbe79bd49,0xbe79bd49,0xbf78bf80,
0x3f4e3f67,0xbf18bedb,0xbf18bedb,0xbf4ebf67,0x3f043f2c,0xbf5cbf3e,0xbf5cbf3e,0xbf04bf2c,0x3e163eac,0xbf7dbf71,0xbf7dbf71,0xbe16beac,
0xbf6fbf7f,0x3eb83d97,0x3f6a3f42,0x3ecf3f27,0xbf13bf4a,0x3f513f1d,0x3f7c3f7e,0xbe2f3dfb,0xbcc9bea1,0x3f803f73,0x3f393f65,0xbf31bee6,
0x3f093e89,0x3f583f77,0x3e603efc,0xbf7abf5f,0x3f623f7f,0xbef1bdc9,0xbf62bf7f,0x3ef13dc9,0x3e953f22,0xbf75bf46,0xbe95bf22,0x3f753f46,
0xbef1bdc9,0xbf62bf7f,0x3ef13dc9,0x3f623f7f,0xbf75bf46,0xbe95bf22,0x3f753f46,0x3e953f22,0xbf51bf7e,0x3f133dfb,0x3e2f3f1d,0xbf7cbf4a,
0x3cc9bee6,0x3f803f65,0xbf39bea1,0xbf31bf73,0x3f583efc,0x3f093f5f,0xbf7abf77,0x3e60be89,0x3f6a3f7f,0xbecf3d97,0xbeb8bf42,0x3f6f3f27,
0x3f3e3f7d,0xbf2cbe16,0x3f2c3e16,0x3f3e3f7d,0xbeac3e79,0xbf71bf78,0x3f713f78,0xbeac3e79,0xbf80bf4e,0xbd49bf18,0x3d493f18,0xbf80bf4e,
0xbedbbf5c,0x3f673f04,0xbf67bf04,0xbedbbf5c,0xbf27bf7c,0x3f423e2f,0xbf7fbf51,0x3d97bf13,0x3f1dbcc9,0x3f4a3f80,0xbdfbbf39,0x3f7e3f31,
0x3f653f7a,0xbee63e60,0x3f733f09,0x3ea13f58,0xbe893ecf,0xbf77bf6a,0x3efc3f6f,0xbf5fbeb8,0x3f0e3f7b,0xbf55be48,0x3f0e3f7b,0xbf55be48,
0xbf55be48,0xbf0ebf7b,0xbf55be48,0xbf0ebf7b,0xbf0ebf7b,0x3f553e48,0xbf0ebf7b,0x3f553e48,0x3f553e48,0x3f0e3f7b,0x3f553e48,0x3f0e3f7b,
0xbee6bf7a,0x3f653e60,0x3ea1bf09,0x3f733f58,0x3f773ecf,0x3e893f6a,0x3f5f3f6f,0xbefc3eb8,0x3d973f51,0xbf7fbf13,0xbf273e2f,0xbf42bf7c,
0xbf7ebf39,0x3dfbbf31,0xbf1dbf80,0x3f4a3cc9,0x3eac3f78,0xbf71be79,0xbf71be79,0xbeacbf78,0xbf80bf18,0x3d49bf4e,0x3d49bf4e,0x3f803f18,
0x3edbbf04,0x3f673f5c,0x3f673f5c,0xbedb3f04,0x3f2c3f7d,0xbf3e3e16,0xbf3e3e16,0xbf2cbf7d,0xbe60bf77,0x3f7a3e89,0x3f583f5f,0xbf093efc,
0x3f6f3f42,0xbeb83f27,0xbf6abd97,0xbecfbf7f,0xbf513dfb,0xbf13bf7e,0x3e2fbf4a,0x3f7c3f1d,0xbcc9bf65,0x3f803ee6,0x3f393f73,0xbf313ea1,
0x3dc93f75,0xbf7fbe95,0xbdc9bf75,0x3f7f3e95,0xbf46bf62,0x3f22bef1,0x3f463f62,0xbf223ef1,0x3f7f3e95,0x3dc93f75,0xbf7fbe95,0xbdc9bf75,
0xbf223ef1,0xbf46bf62,0x3f22bef1,0x3f463f62,0x3cc9bf73,0x3f803ea1,0xbf393ee6,0xbf31bf65,0x3f093f77,0xbf583e89,0x3e60bf5f,0x3f7a3efc,
0xbf6abf27,0x3ecfbf42,0x3eb83f7f,0xbf6f3d97,0x3f7c3dfb,0x3e2f3f7e,0xbf51bf4a,0x3f13bf1d,0xbe163f71,0xbf7dbeac,0x3f7d3eac,0xbe163f71,
0xbe79bf80,0x3f78bd49,0xbf783d49,0xbe79bf80,0x3f183f67,0xbf4e3edb,0x3f4ebedb,0x3f183f67,0xbf5cbf2c,0x3f04bf3e,0xbf043f3e,0xbf5cbf2c,
0x3e89bf6f,0x3f773eb8,0xbefcbf6a,0x3f5fbecf,0xbd973f7c,0xbf7fbe2f,0x3f273f51,0xbf423f13,0xbdfbbf80,0x3f7ebcc9,0xbf4abf31,0x3f1dbf39,
0x3ea13f7a,0xbf733e60,0x3f653f09,0xbee63f58,0xbec43f6d,0xbf6dbec4,0xbec43f6d,0xbf6dbec4,0x3ec4bf6d,0x3f6d3ec4,0x3ec4bf6d,0x3f6d3ec4,
0xbec43f6d,0xbf6dbec4,0xbec43f6d,0xbf6dbec4,0x3ec4bf6d,0x3f6d3ec4,0x3ec4bf6d,0x3f6d3ec4,0x3efcbf6a,0x3f5f3ecf,0x3f77beb8,0x3e893f6f,
0xbf273f51,0xbf42bf13,0xbf7f3e2f,0xbd97bf7c,0x3f4abf31,0x3f1d3f39,0x3f7e3cc9,0xbdfb3f80,0xbf653f09,0xbee6bf58,0xbf73be60,0x3ea1bf7a,
0xbf183f67,0xbf4ebedb,0xbf4ebedb,0x3f18bf67,0x3f5cbf2c,0x3f043f3e,0x3f043f3e,0xbf5c3f2c,0xbf7d3eac,0xbe16bf71,0xbe16bf71,0x3f7dbeac,
0x3f783d49,0xbe793f80,0xbe793f80,0xbf78bd49,0x3f31bf65,0x3f393ee6,0x3cc93f73,0xbf803ea1,0xbf7a3efc,0xbe60bf5f,0x3f09bf77,0x3f583e89,
0x3f6f3d97,0xbeb83f7f,0xbf6a3f27,0xbecfbf42,0xbf13bf1d,0x3f51bf4a,0x3f7cbdfb,0xbe2f3f7e,0xbf463f62,0xbf22bef1,0x3f46bf62,0x3f223ef1,
0x3f7fbe95,0xbdc93f75,0xbf7f3e95,0x3dc9bf75,0xbf22bef1,0x3f46bf62,0x3f223ef1,0xbf463f62,0xbdc93f75,0xbf7f3e95,0x3dc9bf75,0x3f7fbe95,
0x3f58bf5f,0x3f093efc,0xbf7a3e89,0x3e60bf77,0xbf6a3d97,0x3ecfbf7f,0x3eb83f27,0xbf6f3f42,0x3e2f3f4a,0xbf7c3f1d,0x3f13bf7e,0x3f513dfb,
0x3f39bf73,0x3f313ea1,0xbf803ee6,0x3cc9bf65,0xbf673f5c,0xbedbbf04,0x3edb3f04,0xbf673f5c,0x3f3e3e16,0xbf2c3f7d,0x3f2cbf7d,0x3f3e3e16,
0x3eacbf78,0x3f71be79,0xbf713e79,0x3eacbf78,0xbf803f18,0xbd49bf4e,0x3d493f4e,0xbf803f18,0x3f73bf58,0x3ea13f09,0x3ee6bf7a,0x3f65be60,
0xbefcbeb8,0x3f5fbf6f,0xbf773ecf,0x3e89bf6a,0xbf423f7c,0xbf27be2f,0xbd973f51,0xbf7f3f13,0x3f4abcc9,0xbf1d3f80,0x3f7ebf39,0x3dfb3f31,
0xbf7b3f55,0xbe48bf0e,0xbf7b3f55,0xbe48bf0e,0x3e483f0e,0xbf7b3f55,0x3e483f0e,0xbf7b3f55,0x3f7bbf55,0x3e483f0e,0x3f7bbf55,0x3e483f0e,
0xbe48bf0e,0x3f7bbf55,0xbe48bf0e,0x3f7bbf55,0x3f7fbf51,0x3d973f13,0x3f42be2f,0xbf273f7c,0x3dfbbf39,0x3f7ebf31,0x3f4abf80,0x3f1d3cc9,
0xbf733f09,0x3ea1bf58,0xbee6be60,0x3f65bf7a,0xbefc3f6f,0xbf5f3eb8,0xbf773f6a,0xbe89becf,0xbf803f4e,0x3d49bf18,0x3d49bf18,0x3f80bf4e,
0xbedb3f5c,0xbf673f04,0xbf673f04,0x3edbbf5c,0x3f2cbe16,0xbf3e3f7d,0xbf3e3f7d,0xbf2c3e16,0x3f71bf78,0x3eac3e79,0x3eac3e79,0xbf713f78,
0x3f7cbf4a,0xbe2f3f1d,0xbf513f7e,0xbf133dfb,0x3f31bf73,0x3f39bea1,0x3cc93ee6,0xbf803f65,0xbe60be89,0x3f7abf77,0x3f58befc,0xbf093f5f,
0xbf6f3f27,0x3eb8bf42,0x3f6abf7f,0x3ecf3d97,0xbf753f46,0x3e95bf22,0x3f75bf46,0xbe953f22,0xbf623f7f,0xbef13dc9,0x3f62bf7f,0x3ef1bdc9,
0xbe953f22,0xbf753f46,0x3e95bf22,0x3f75bf46,0x3ef1bdc9,0xbf623f7f,0xbef13dc9,0x3f62bf7f,0x3f6abf42,0xbecf3f27,0xbeb83d97,0x3f6fbf7f,
0x3f7cbf7e,0x3e2f3dfb,0xbf513f1d,0x3f13bf4a,0x3f39bf65,0x3f31bee6,0xbf803f73,0x3cc9bea1,0x3e60befc,0x3f7abf5f,0xbf583f77,0xbf093e89,
0xbf5c3f3e,0x3f04bf2c,0xbf043f2c,0xbf5c3f3e,0xbf7d3f71,0x3e16beac,0xbe163eac,0xbf7d3f71,0xbf783f80,0xbe793d49,0x3e79bd49,0xbf783f80,
0xbf4e3f67,0xbf183edb,0x3f18bedb,0xbf4e3f67,0x3f4abf39,0xbf1d3f31,0x3f7ebf80,0x3dfbbcc9,0x3f65bf58,0xbee63f09,0x3f73bf7a,0x3ea1be60,
0x3f77bf6f,0xbe893eb8,0x3f5fbf6a,0x3efcbecf,0x3f7fbf7c,0xbd973e2f,0x3f42bf51,0x3f27bf13,0x3f803f80,0xbf353f35,0x3f803f80,0xbf353f35,
0x3f803f80,0xbf353f35,0x3f803f80,0xbf353f35,0x3f803f80,0xbf353f35,0x3f803f80,0xbf353f35,0x3f803f80,0xbf353f35,0x3f803f80,0xbf353f35,
0x3dfb3cc9,0x3f7e3f80,0x3f4a3f39,0x3f1d3f31,0x3ea13e60,0x3f733f7a,0x3f653f58,0x3ee63f09,0x3efc3ecf,0x3f5f3f6a,0x3f773f6f,0x3e893eb8,
0x3f273f13,0x3f423f51,0x3f7f3f7c,0x3d973e2f,0xbf78bf80,0x3e793d49,0x3e793d49,0x3f783f80,0xbf4ebf67,0x3f183edb,0x3f183edb,0x3f4e3f67,
0xbf04bf2c,0x3f5c3f3e,0x3f5c3f3e,0x3f043f2c,0xbe16beac,0x3f7d3f71,0x3f7d3f71,0x3e163eac,0xbeb8bd97,0xbf6fbf7f,0xbecfbf27,0x3f6a3f42,
0xbf51bf1d,0xbf13bf4a,0x3e2fbdfb,0x3f7c3f7e,0xbf80bf73,0xbcc9bea1,0x3f313ee6,0x3f393f65,0xbf58bf77,0x3f093e89,0x3f7a3f5f,0x3e603efc,
0x3f623f7f,0xbef1bdc9,0xbf62bf7f,0x3ef13dc9,0x3e953f22,0xbf75bf46,0xbe95bf22,0x3f753f46,0xbef1bdc9,0xbf62bf7f,0x3ef13dc9,0x3f623f7f,
0xbf75bf46,0xbe95bf22,0x3f753f46,0x3e953f22,0x3f133dfb,0x3f513f7e,0xbf7cbf4a,0xbe2fbf1d,0x3f803f65,0xbcc93ee6,0xbf31bf73,0x3f393ea1,
0x3f093f5f,0xbf58befc,0x3e60be89,0x3f7a3f77,0xbecf3d97,0xbf6abf7f,0x3f6f3f27,0x3eb83f42,0xbf3ebf7d,0x3f2c3e16,0xbf2cbe16,0xbf3ebf7d,
0x3eacbe79,0x3f713f78,0xbf71bf78,0x3eacbe79,0x3f803f4e,0x3d493f18,0xbd49bf18,0x3f803f4e,0x3edb3f5c,0xbf67bf04,0x3f673f04,0x3edb3f5c,
0xbf42be2f,0xbf27bf7c,0xbd973f13,0xbf7fbf51,0xbf4abf80,0x3f1dbcc9,0xbf7ebf31,0xbdfbbf39,0x3ee6be60,0x3f653f7a,0xbea1bf58,0x3f733f09,
0x3f773f6a,0xbe893ecf,0x3f5f3eb8,0x3efc3f6f,0x3f0e3f7b,0xbf55be48,0x3f0e3f7b,0xbf55be48,0xbf55be48,0xbf0ebf7b,0xbf55be48,0xbf0ebf7b,
0xbf0ebf7b,0x3f553e48,0xbf0ebf7b,0x3f553e48,0x3f553e48,0x3f0e3f7b,0x3f553e48,0x3f0e3f7b,0x3f653e60,0x3ee63f7a,0x3f733f58,0xbea13f09,
0x3e893f6a,0xbf77becf,0xbefc3eb8,0xbf5fbf6f,0xbf7fbf13,0xbd97bf51,0xbf42bf7c,0x3f27be2f,0x3dfbbf31,0x3f7e3f39,0x3f4a3cc9,0x3f1d3f80,
0xbeacbf78,0x3f713e79,0x3f713e79,0x3eac3f78,0x3f803f18,0xbd493f4e,0xbd493f4e,0xbf80bf18,0xbedb3f04,0xbf67bf5c,0xbf67bf5c,0x3edbbf04,
0xbf2cbf7d,0x3f3ebe16,0x3f3ebe16,0x3f2c3f7d,0xbf7abe89,0xbe60bf77,0x3f09befc,0x3f583f5f,0x3eb8bf27,0x3f6f3f42,0x3ecf3f7f,0xbf6abd97,
0x3f133f7e,0xbf513dfb,0xbf7cbf1d,0x3e2fbf4a,0xbf80bee6,0xbcc9bf65,0x3f31bea1,0x3f393f73,0x3dc93f75,0xbf7fbe95,0xbdc9bf75,0x3f7f3e95,
0xbf46bf62,0x3f22bef1,0x3f463f62,0xbf223ef1,0x3f7f3e95,0x3dc93f75,0xbf7fbe95,0xbdc9bf75,0xbf223ef1,0xbf46bf62,0x3f22bef1,0x3f463f62,
0x3f803ea1,0xbcc93f73,0xbf31bf65,0x3f39bee6,0xbf583e89,0xbf09bf77,0x3f7a3efc,0xbe603f5f,0x3ecfbf42,0x3f6a3f27,0xbf6f3d97,0xbeb8bf7f,
0x3e2f3f7e,0xbf7cbdfb,0x3f13bf1d,0x3f513f4a,0x3e16bf71,0x3f7d3eac,0xbf7dbeac,0x3e16bf71,0x3e793f80,0xbf783d49,0x3f78bd49,0x3e793f80,
0xbf18bf67,0x3f4ebedb,0xbf4e3edb,0xbf18bf67,0x3f5c3f2c,0xbf043f3e,0x3f04bf3e,0x3f5c3f2c,0xbf77beb8,0x3e89bf6f,0xbf5f3ecf,0xbefcbf6a,
0x3f7f3e2f,0xbd973f7c,0x3f42bf13,0x3f273f51,0xbf7e3cc9,0xbdfbbf80,0xbf1d3f39,0xbf4abf31,0x3f73be60,0x3ea13f7a,0x3ee6bf58,0x3f653f09,
0xbec43f6d,0xbf6dbec4,0xbec43f6d,0xbf6dbec4,0x3ec4bf6d,0x3f6d3ec4,0x3ec4bf6d,0x3f6d3ec4,0xbec43f6d,0xbf6dbec4,0xbec43f6d,0xbf6dbec4,
0x3ec4bf6d,0x3f6d3ec4,0x3ec4bf6d,0x3f6d3ec4,0x3f5f3ecf,0xbefc3f6a,0x3e893f6f,0xbf773eb8,0xbf42bf13,0x3f27bf51,0xbd97bf7c,0x3f7fbe2f,
0x3f1d3f39,0xbf4a3f31,0xbdfb3f80,0xbf7ebcc9,0xbee6bf58,0x3f65bf09,0x3ea1bf7a,0x3f733e60,0x3f18bf67,0x3f4e3edb,0x3f4e3edb,0xbf183f67,
0xbf5c3f2c,0xbf04bf3e,0xbf04bf3e,0x3f5cbf2c,0x3f7dbeac,0x3e163f71,0x3e163f71,0xbf7d3eac,0xbf78bd49,0x3e79bf80,0x3e79bf80,0x3f783d49,
0xbf39bee6,0x3f31bf65,0x3f80bea1,0x3cc93f73,0x3e603f5f,0xbf7a3efc,0xbf58be89,0x3f09bf77,0x3eb8bf7f,0x3f6f3d97,0x3ecf3f42,0xbf6a3f27,
0xbf513f4a,0xbf13bf1d,0x3e2fbf7e,0x3f7cbdfb,0xbf463f62,0xbf22bef1,0x3f46bf62,0x3f223ef1,0x3f7fbe95,0xbdc93f75,0xbf7f3e95,0x3dc9bf75,
0xbf22bef1,0x3f46bf62,0x3f223ef1,0xbf463f62,0xbdc93f75,0xbf7f3e95,0x3dc9bf75,0x3f7fbe95,0x3f093efc,0xbf583f5f,0x3e60bf77,0x3f7abe89,
0x3ecfbf7f,0x3f6abd97,0xbf6f3f42,0xbeb8bf27,0xbf7c3f1d,0xbe2fbf4a,0x3f513dfb,0xbf133f7e,0x3f313ea1,0xbf393f73,0x3cc9bf65,0x3f80bee6,
0x3f67bf5c,0x3edb3f04,0xbedbbf04,0x3f67bf5c,0xbf3ebe16,0x3f2cbf7d,0xbf2c3f7d,0xbf3ebe16,0xbeac3f78,0xbf713e79,0x3f71be79,0xbeac3f78,
0x3f80bf18,0x3d493f4e,0xbd49bf4e,0x3f80bf18,0xbea1bf09,0x3f73bf58,0xbf653e60,0x3ee6bf7a,0xbf5f3f6f,0xbefcbeb8,0xbe893f6a,0xbf773ecf,
0x3f273e2f,0xbf423f7c,0x3f7fbf13,0xbd973f51,0x3f1dbf80,0x3f4abcc9,0xbdfbbf31,0x3f7ebf39,0xbf7b3f55,0xbe48bf0e,0xbf7b3f55,0xbe48bf0e,
0x3e483f0e,0xbf7b3f55,0x3e483f0e,0xbf7b3f55,0x3f7bbf55,0x3e483f0e,0x3f7bbf55,0x3e483f0e,0xbe48bf0e,0x3f7bbf55,0xbe48bf0e,0x3f7bbf55,
0x3d973f13,0xbf7f3f51,0xbf273f7c,0xbf423e2f,0x3f7ebf31,0xbdfb3f39,0x3f1d3cc9,0xbf4a3f80,0x3ea1bf58,0x3f73bf09,0x3f65bf7a,0x3ee63e60,
0xbf5f3eb8,0x3efcbf6f,0xbe89becf,0x3f77bf6a,0x3f80bf4e,0xbd493f18,0xbd493f18,0xbf803f4e,0x3edbbf5c,0x3f67bf04,0x3f67bf04,0xbedb3f5c,
0xbf2c3e16,0x3f3ebf7d,0x3f3ebf7d,0x3f2cbe16,0xbf713f78,0xbeacbe79,0xbeacbe79,0x3f71bf78,0x3e2fbf1d,0x3f7cbf4a,0x3f13bdfb,0xbf513f7e,
0xbf393ea1,0x3f31bf73,0x3f80bf65,0x3cc93ee6,0xbf7a3f77,0xbe60be89,0x3f09bf5f,0x3f58befc,0xbeb83f42,0xbf6f3f27,0xbecfbd97,0x3f6abf7f,
0xbf753f46,0x3e95bf22,0x3f75bf46,0xbe953f22,0xbf623f7f,0xbef13dc9,0x3f62bf7f,0x3ef1bdc9,0xbe953f22,0xbf753f46,0x3e95bf22,0x3f75bf46,
0x3ef1bdc9,0xbf623f7f,0xbef13dc9,0x3f62bf7f,0xbecf3f27,0xbf6a3f42,0x3f6fbf7f,0x3eb8bd97,0x3e2f3dfb,0xbf7c3f7e,0x3f13bf4a,0x3f51bf1d,
0x3f31bee6,0xbf393f65,0x3cc9bea1,0x3f80bf73,0x3f7abf5f,0xbe603efc,0xbf093e89,0x3f58bf77,0x3f5cbf3e,0xbf043f2c,0x3f04bf2c,0x3f5cbf3e,
0x3f7dbf71,0xbe163eac,0x3e16beac,0x3f7dbf71,0x3f78bf80,0x3e79bd49,0xbe793d49,0x3f78bf80,0x3f4ebf67,0x3f18bedb,0xbf183edb,0x3f4ebf67,
0x3f1dbf31,0x3f4abf39,0xbdfb3cc9,0x3f7ebf80,0x3ee6bf09,0x3f65bf58,0xbea13e60,0x3f73bf7a,0x3e89beb8,0x3f77bf6f,0xbefc3ecf,0x3f5fbf6a,
0x3d97be2f,0x3f7fbf7c,0xbf273f13,0x3f42bf51,0x3f803f80,0xbf803f80,0x3f803f80,0xbf803f80,0x3f803f80,0xbf803f80,0x3f803f80,0xbf803f80,
0x3f803f80,0xbf803f80,0x3f803f80,0xbf803f80,0x3f803f80,0xbf803f80,0x3f803f80,0xbf803f80,0x3f7d3f80,0xbe16bd49,0x3f183f2c,0xbf4ebf3e,
0x3f713f78,0xbeacbe79,0x3edb3f04,0xbf67bf5c,0x3f5c3f67,0xbf04bedb,0x3e793eac,0xbf78bf71,0x3f3e3f4e,0xbf2cbf18,0x3d493e16,0xbf80bf7d,
0x3f753f7f,0xbe95bdc9,0xbe95bdc9,0xbf75bf7f,0x3f463f62,0xbf22bef1,0xbf22bef1,0xbf46bf62,0x3ef13f22,0xbf62bf46,0xbf62bf46,0xbef1bf22,
0x3dc93e95,0xbf7fbf75,0xbf7fbf75,0xbdc9be95,0x3f673f7d,0xbedbbe16,0xbf71bf4e,0xbeacbf18,0x3f043f3e,0xbf5cbf2c,0xbf78bf80,0x3e79bd49,
0xbd493e79,0xbf80bf78,0xbf2cbf5c,0x3f3e3f04,0xbf18beac,0xbf4ebf71,0xbe16bedb,0x3f7d3f67,0x3f553f7b,0xbf0ebe48,0xbf55bf7b,0x3f0e3e48,
0x3e483f0e,0xbf7bbf55,0xbe48bf0e,0x3f7b3f55,0xbf0ebe48,0xbf55bf7b,0x3f0e3e48,0x3f553f7b,0xbf7bbf55,0xbe48bf0e,0x3f7b3f55,0x3e483f0e,
0x3f3e3f78,0xbf2cbe79,0xbd49bf04,0x3f803f5c,0xbe163eac,0xbf7dbf71,0x3f4e3edb,0x3f183f67,0xbf67bf18,0xbedbbf4e,0x3f713f7d,0xbeac3e16,
0xbf5cbf80,0x3f043d49,0x3e793f2c,0xbf78bf3e,0x3f223f75,0xbf46be95,0x3f463e95,0x3f223f75,0xbef13dc9,0xbf62bf7f,0x3f623f7f,0xbef13dc9,
0xbf7fbf62,0x3dc9bef1,0xbdc93ef1,0xbf7fbf62,0xbe95bf46,0x3f753f22,0xbf75bf22,0xbe95bf46,0x3f043f71,0xbf5cbeac,0x3f783f67,0xbe793edb,
0xbf3ebe16,0xbf2cbf7d,0xbd493f18,0xbf80bf4e,0xbf4ebf80,0x3f18bd49,0xbf7dbf2c,0xbe16bf3e,0x3edbbe79,0x3f673f78,0xbeacbf5c,0x3f713f04,
0x3ec43f6d,0xbf6dbec4,0x3ec43f6d,0xbf6dbec4,0xbf6dbec4,0xbec4bf6d,0xbf6dbec4,0xbec4bf6d,0xbec4bf6d,0x3f6d3ec4,0xbec4bf6d,0x3f6d3ec4,
0x3f6d3ec4,0x3ec43f6d,0x3f6d3ec4,0x3ec43f6d,0x3e793f67,0xbf78bedb,0xbf043eac,0xbf5cbf71,0xbf80bf18,0xbd49bf4e,0xbf3ebf7d,0x3f2cbe16,
0x3e16bf2c,0x3f7d3f3e,0x3f4e3d49,0x3f183f80,0x3f713f5c,0xbeac3f04,0x3edb3f78,0xbf67be79,0x3dc93f62,0xbf7fbef1,0xbf7fbef1,0xbdc9bf62,
0xbf75bf46,0x3e95bf22,0x3e95bf22,0x3f753f46,0x3f22be95,0x3f463f75,0x3f463f75,0xbf223e95,0x3ef13f7f,0xbf62bdc9,0xbf62bdc9,0xbef1bf7f,
0xbd493f5c,0xbf80bf04,0xbf2cbf78,0x3f3ebe79,0xbf4ebf67,0x3f18bedb,0x3f7d3eac,0x3e163f71,0x3f713e16,0x3eac3f7d,0xbedb3f18,0xbf67bf4e,
0xbe793f3e,0xbf78bf2c,0xbf04bf80,0x3f5cbd49,0xbe483f55,0xbf7bbf0e,0x3e48bf55,0x3f7b3f0e,0xbf0ebf7b,0x3f55be48,0x3f0e3f7b,0xbf553e48,
0x3f7b3f0e,0xbe483f55,0xbf7bbf0e,0x3e48bf55,0xbf553e48,0xbf0ebf7b,0x3f55be48,0x3f0e3f7b,0xbeac3f4e,0xbf71bf18,0x3f67be16,0x3edb3f7d,
0xbe79bf80,0x3f783d49,0xbf043f2c,0xbf5cbf3e,0x3f3e3f5c,0xbf2c3f04,0xbd49bf78,0x3f803e79,0xbf7dbedb,0x3e16bf67,0x3f183f71,0xbf4e3eac,
0xbef13f46,0xbf62bf22,0x3f623f22,0xbef13f46,0x3dc9bf75,0x3f7f3e95,0xbf7fbe95,0x3dc9bf75,0x3e953f7f,0xbf753dc9,0x3f75bdc9,0x3e953f7f,
0xbf22bf62,0x3f46bef1,0xbf463ef1,0xbf22bf62,0xbf183f3e,0xbf4ebf2c,0x3e163f80,0xbf7d3d49,0x3edbbf5c,0x3f673f04,0xbeacbf78,0x3f71be79,
0xbe793f71,0xbf78beac,0x3f043f67,0xbf5c3edb,0x3d49bf7d,0x3f803e16,0xbf2cbf4e,0x3f3ebf18,0xbf353f35,0xbf35bf35,0xbf353f35,0xbf35bf35,
0x3f35bf35,0x3f353f35,0x3f35bf35,0x3f353f35,0xbf353f35,0xbf35bf35,0xbf353f35,0xbf35bf35,0x3f35bf35,0x3f353f35,0x3f35bf35,0x3f353f35,
0xbf4e3f2c,0xbf18bf3e,0xbf7dbd49,0x3e16bf80,0x3f67bf04,0x3edb3f5c,0x3f713e79,0xbeac3f78,0xbf783eac,0xbe79bf71,0xbf5cbedb,0x3f04bf67,
0x3f80be16,0x3d493f7d,0x3f3e3f18,0xbf2c3f4e,0xbf623f22,0xbef1bf46,0xbef1bf46,0x3f62bf22,0x3f7fbe95,0x3dc93f75,0x3dc93f75,0xbf7f3e95,
0xbf75bdc9,0x3e95bf7f,0x3e95bf7f,0x3f753dc9,0x3f463ef1,0xbf223f62,0xbf223f62,0xbf46bef1,0xbf713f18,0xbeacbf4e,0x3edbbf7d,0x3f673e16,
0x3f78bd49,0xbe793f80,0xbf5c3f3e,0xbf04bf2c,0xbf2cbf04,0x3f3ebf5c,0x3f80be79,0xbd493f78,0x3e163f67,0xbf7d3edb,0xbf4ebeac,0x3f18bf71,
0xbf7b3f0e,0xbe48bf55,0x3f7bbf0e,0x3e483f55,0x3f553e48,0xbf0e3f7b,0xbf55be48,0x3f0ebf7b,0xbe48bf55,0x3f7bbf0e,0x3e483f55,0xbf7b3f0e,
0xbf0e3f7b,0xbf55be48,0x3f0ebf7b,0x3f553e48,0xbf803f04,0xbd49bf5c,0x3f3e3e79,0xbf2c3f78,0x3f183edb,0xbf4e3f67,0x3e16bf71,0x3f7dbeac,
0x3eacbf7d,0x3f71be16,0xbf673f4e,0xbedbbf18,0xbf783f2c,0xbe79bf3e,0x3f5c3d49,0xbf043f80,0xbf7f3ef1,0x3dc9bf62,0xbdc93f62,0xbf7f3ef1,
0x3e953f22,0xbf753f46,0x3f75bf46,0x3e953f22,0x3f46bf75,0x3f223e95,0xbf22be95,0x3f46bf75,0xbf623dc9,0x3ef1bf7f,0xbef13f7f,0xbf623dc9,
0xbf783edb,0x3e79bf67,0xbf5c3f71,0xbf04beac,0xbd493f4e,0xbf803f18,0x3f2c3e16,0xbf3e3f7d,0x3f7dbf3e,0x3e163f2c,0x3f18bf80,0x3f4ebd49,
0xbeacbf04,0x3f71bf5c,0xbf673e79,0x3edbbf78,0xbf6d3ec4,0x3ec4bf6d,0xbf6d3ec4,0x3ec4bf6d,0xbec43f6d,0xbf6d3ec4,0xbec43f6d,0xbf6d3ec4,
0x3f6dbec4,0xbec43f6d,0x3f6dbec4,0xbec43f6d,0x3ec4bf6d,0x3f6dbec4,0x3ec4bf6d,0x3f6dbec4,0xbf5c3eac,0x3f04bf71,0xbe79bedb,0x3f78bf67,
0xbf2c3f7d,0xbf3e3e16,0xbf803f4e,0xbd49bf18,0x3f183d49,0xbf4e3f80,0xbe163f3e,0xbf7d3f2c,0x3f67bf78,0x3edb3e79,0x3f71bf04,0xbeac3f5c,
0xbf463e95,0x3f22bf75,0x3f22bf75,0x3f46be95,0xbf623f7f,0xbef1bdc9,0xbef1bdc9,0x3f62bf7f,0x3dc93ef1,0xbf7f3f62,0xbf7f3f62,0xbdc9bef1,
0x3f75bf22,0xbe953f46,0xbe953f46,0xbf753f22,0xbf2c3e79,0x3f3ebf78,0x3f80bf5c,0xbd493f04,0xbf7d3f71,0xbe16beac,0x3f18bf67,0x3f4ebedb,
0xbedb3f4e,0xbf673f18,0xbeacbe16,0x3f71bf7d,0x3f04bd49,0xbf5c3f80,0xbf783f3e,0x3e79bf2c,0xbf0e3e48,0x3f55bf7b,0x3f0ebe48,0xbf553f7b,
0xbf7b3f55,0x3e48bf0e,0x3f7bbf55,0xbe483f0e,0xbf553f7b,0xbf0e3e48,0x3f55bf7b,0x3f0ebe48,0xbe483f0e,0xbf7b3f55,0x3e48bf0e,0x3f7bbf55,
0xbedb3e16,0x3f67bf7d,0xbeac3f18,0xbf713f4e,0xbf5c3f2c,0x3f04bf3e,0x3e793d49,0xbf783f80,0xbf803f78,0xbd49be79,0x3f3ebf04,0xbf2c3f5c,
0xbf4e3f71,0xbf183eac,0x3f7dbf67,0xbe163edb,0xbe953dc9,0x3f75bf7f,0xbf753f7f,0xbe953dc9,0xbf223ef1,0x3f46bf62,0xbf463f62,0xbf223ef1,
0xbf623f46,0x3ef1bf22,0xbef13f22,0xbf623f46,0xbf7f3f75,0x3dc9be95,0xbdc93e95,0xbf7f3f75,0xbe163d49,0x3f7dbf80,0xbf4e3f3e,0x3f18bf2c,
0xbeac3e79,0x3f71bf78,0xbf673f5c,0x3edbbf04,0xbf043edb,0x3f5cbf67,0xbf783f71,0x3e79beac,0xbf2c3f18,0x3f3ebf4e,0xbf803f7d,0x3d49be16,
0x3f803f80,0xbf803f80,0x3f803f80,0xbf803f80,0x3f803f80,0xbf803f80,0x3f803f80,0xbf803f80,0x3f803f80,0xbf803f80,0x3f803f80,0xbf803f80,
0x3f803f80,0xbf803f80,0x3f803f80,0xbf803f80,0xbe16bd49,0xbf7dbf80,0xbf4ebf3e,0xbf18bf2c,0xbeacbe79,0xbf71bf78,0xbf67bf5c,0xbedbbf04,
0xbf04bedb,0xbf5cbf67,0xbf78bf71,0xbe79beac,0xbf2cbf18,0xbf3ebf4e,0xbf80bf7d,0xbd49be16,0xbf75bf7f,0x3e953dc9,0x3e953dc9,0x3f753f7f,
0xbf46bf62,0x3f223ef1,0x3f223ef1,0x3f463f62,0xbef1bf22,0x3f623f46,0x3f623f46,0x3ef13f22,0xbdc9be95,0x3f7f3f75,0x3f7f3f75,0x3dc93e95,
0x3edb3e16,0x3f673f7d,0x3eac3f18,0xbf71bf4e,0x3f5c3f2c,0x3f043f3e,0xbe793d49,0xbf78bf80,0x3f803f78,0xbd493e79,0xbf3ebf04,0xbf2cbf5c,
0x3f4e3f71,0xbf18beac,0xbf7dbf67,0xbe16bedb,0x3f553f7b,0xbf0ebe48,0xbf55bf7b,0x3f0e3e48,0x3e483f0e,0xbf7bbf55,0xbe48bf0e,0x3f7b3f55,
0xbf0ebe48,0xbf55bf7b,0x3f0e3e48,0x3f553f7b,0xbf7bbf55,0xbe48bf0e,0x3f7b3f55,0x3e483f0e,0xbf2cbe79,0xbf3ebf78,0x3f803f5c,0x3d493f04,
0xbf7dbf71,0x3e16beac,0x3f183f67,0xbf4ebedb,0xbedbbf4e,0x3f673f18,0xbeac3e16,0xbf71bf7d,0x3f043d49,0x3f5c3f80,0xbf78bf3e,0xbe79bf2c,
0xbf22bf75,0x3f463e95,0xbf46be95,0xbf22bf75,0x3ef1bdc9,0x3f623f7f,0xbf62bf7f,0x3ef1bdc9,0x3f7f3f62,0xbdc93ef1,0x3dc9bef1,0x3f7f3f62,
0x3e953f46,0xbf75bf22,0x3f753f22,0x3e953f46,0x3f5c3eac,0x3f043f71,0x3e79bedb,0x3f783f67,0x3f2c3f7d,0xbf3ebe16,0x3f803f4e,0xbd493f18,
0xbf183d49,0xbf4ebf80,0x3e163f3e,0xbf7dbf2c,0xbf67bf78,0x3edbbe79,0xbf71bf04,0xbeacbf5c,0x3ec43f6d,0xbf6dbec4,0x3ec43f6d,0xbf6dbec4,
0xbf6dbec4,0xbec4bf6d,0xbf6dbec4,0xbec4bf6d,0xbec4bf6d,0x3f6d3ec4,0xbec4bf6d,0x3f6d3ec4,0x3f6d3ec4,0x3ec43f6d,0x3f6d3ec4,0x3ec43f6d,
0xbf78bedb,0xbe79bf67,0xbf5cbf71,0x3f04beac,0xbd49bf4e,0x3f803f18,0x3f2cbe16,0x3f3e3f7d,0x3f7d3f3e,0xbe163f2c,0x3f183f80,0xbf4ebd49,
0xbeac3f04,0xbf71bf5c,0xbf67be79,0xbedbbf78,0xbdc9bf62,0x3f7f3ef1,0x3f7f3ef1,0x3dc93f62,0x3f753f46,0xbe953f22,0xbe953f22,0xbf75bf46,
0xbf223e95,0xbf46bf75,0xbf46bf75,0x3f22be95,0xbef1bf7f,0x3f623dc9,0x3f623dc9,0x3ef13f7f,0x3f803f04,0xbd493f5c,0xbf3e3e79,0xbf2cbf78,
0xbf183edb,0xbf4ebf67,0xbe16bf71,0x3f7d3eac,0xbeacbf7d,0x3f713e16,0x3f673f4e,0xbedb3f18,0x3f783f2c,0xbe793f3e,0xbf5c3d49,0xbf04bf80,
0xbe483f55,0xbf7bbf0e,0x3e48bf55,0x3f7b3f0e,0xbf0ebf7b,0x3f55be48,0x3f0e3f7b,0xbf553e48,0x3f7b3f0e,0xbe483f55,0xbf7bbf0e,0x3e48bf55,
0xbf553e48,0xbf0ebf7b,0x3f55be48,0x3f0e3f7b,0xbf71bf18,0x3eacbf4e,0x3edb3f7d,0xbf673e16,0x3f783d49,0x3e793f80,0xbf5cbf3e,0x3f04bf2c,
0xbf2c3f04,0xbf3ebf5c,0x3f803e79,0x3d493f78,0x3e16bf67,0x3f7d3edb,0xbf4e3eac,0xbf18bf71,0x3ef1bf46,0x3f623f22,0xbf62bf22,0x3ef1bf46,
0xbdc93f75,0xbf7fbe95,0x3f7f3e95,0xbdc93f75,0xbe95bf7f,0x3f75bdc9,0xbf753dc9,0xbe95bf7f,0x3f223f62,0xbf463ef1,0x3f46bef1,0x3f223f62,
0x3f4e3f2c,0xbf183f3e,0x3f7dbd49,0x3e163f80,0xbf67bf04,0x3edbbf5c,0xbf713e79,0xbeacbf78,0x3f783eac,0xbe793f71,0x3f5cbedb,0x3f043f67,
0xbf80be16,0x3d49bf7d,0xbf3e3f18,0xbf2cbf4e,0xbf353f35,0xbf35bf35,0xbf353f35,0xbf35bf35,0x3f35bf35,0x3f353f35,0x3f35bf35,0x3f353f35,
0xbf353f35,0xbf35bf35,0xbf353f35,0xbf35bf35,0x3f35bf35,0x3f353f35,0x3f35bf35,0x3f353f35,0xbf18bf3e,0x3f4ebf2c,0x3e16bf80,0x3f7d3d49,
0x3edb3f5c,0xbf673f04,0xbeac3f78,0xbf71be79,0xbe79bf71,0x3f78beac,0x3f04bf67,0x3f5c3edb,0x3d493f7d,0xbf803e16,0xbf2c3f4e,0xbf3ebf18,
0x3f62bf22,0x3ef13f46,0x3ef13f46,0xbf623f22,0xbf7f3e95,0xbdc9bf75,0xbdc9bf75,0x3f7fbe95,0x3f753dc9,0xbe953f7f,0xbe953f7f,0xbf75bdc9,
0xbf46bef1,0x3f22bf62,0x3f22bf62,0x3f463ef1,0x3eac3f4e,0xbf713f18,0xbf67be16,0x3edbbf7d,0x3e79bf80,0x3f78bd49,0x3f043f2c,0xbf5c3f3e,
0xbf3e3f5c,0xbf2cbf04,0x3d49bf78,0x3f80be79,0x3f7dbedb,0x3e163f67,0xbf183f71,0xbf4ebeac,0xbf7b3f0e,0xbe48bf55,0x3f7bbf0e,0x3e483f55,
0x3f553e48,0xbf0e3f7b,0xbf55be48,0x3f0ebf7b,0xbe48bf55,0x3f7bbf0e,0x3e483f55,0xbf7b3f0e,0xbf0e3f7b,0xbf55be48,0x3f0ebf7b,0x3f553e48,
0xbd49bf5c,0x3f80bf04,0xbf2c3f78,0xbf3ebe79,0xbf4e3f67,0xbf18bedb,0x3f7dbeac,0xbe163f71,0x3f71be16,0xbeac3f7d,0xbedbbf18,0x3f67bf4e,
0xbe79bf3e,0x3f78bf2c,0xbf043f80,0xbf5cbd49,0x3f7fbef1,0xbdc93f62,0x3dc9bf62,0x3f7fbef1,0xbe95bf22,0x3f75bf46,0xbf753f46,0xbe95bf22,
0xbf463f75,0xbf22be95,0x3f223e95,0xbf463f75,0x3f62bdc9,0xbef13f7f,0x3ef1bf7f,0x3f62bdc9,0xbe793f67,0xbf783edb,0x3f043eac,0xbf5c3f71,
0x3f80bf18,0xbd493f4e,0x3f3ebf7d,0x3f2c3e16,0xbe16bf2c,0x3f7dbf3e,0xbf4e3d49,0x3f18bf80,0xbf713f5c,0xbeacbf04,0xbedb3f78,0xbf673e79,
0xbf6d3ec4,0x3ec4bf6d,0xbf6d3ec4,0x3ec4bf6d,0xbec43f6d,0xbf6d3ec4,0xbec43f6d,0xbf6d3ec4,0x3f6dbec4,0xbec43f6d,0x3f6dbec4,0xbec43f6d,
0x3ec4bf6d,0x3f6dbec4,0x3ec4bf6d,0x3f6dbec4,0x3f04bf71,0x3f5cbeac,0x3f78bf67,0x3e793edb,0xbf3e3e16,0x3f2cbf7d,0xbd49bf18,0x3f80bf4e,
0xbf4e3f80,0xbf18bd49,0xbf7d3f2c,0x3e16bf3e,0x3edb3e79,0xbf673f78,0xbeac3f5c,0xbf713f04,0x3f46be95,0xbf223f75,0xbf223f75,0xbf463e95,
0x3f62bf7f,0x3ef13dc9,0x3ef13dc9,0xbf623f7f,0xbdc9bef1,0x3f7fbf62,0x3f7fbf62,0x3dc93ef1,0xbf753f22,0x3e95bf46,0x3e95bf46,0x3f75bf22,
0xbf3e3f78,0xbf2c3e79,0x3d49bf04,0x3f80bf5c,0x3e163eac,0xbf7d3f71,0xbf4e3edb,0x3f18bf67,0x3f67bf18,0xbedb3f4e,0xbf713f7d,0xbeacbe16,
0x3f5cbf80,0x3f04bd49,0xbe793f2c,0xbf783f3e,0xbf0e3e48,0x3f55bf7b,0x3f0ebe48,0xbf553f7b,0xbf7b3f55,0x3e48bf0e,0x3f7bbf55,0xbe483f0e,
0xbf553f7b,0xbf0e3e48,0x3f55bf7b,0x3f0ebe48,0xbe483f0e,0xbf7b3f55,0x3e48bf0e,0x3f7bbf55,0x3f67bf7d,0x3edbbe16,0xbf713f4e,0x3eacbf18,
0x3f04bf3e,0x3f5cbf2c,0xbf783f80,0xbe79bd49,0xbd49be79,0x3f80bf78,0xbf2c3f5c,0xbf3e3f04,0xbf183eac,0x3f4ebf71,0xbe163edb,0xbf7d3f67,
0x3e95bdc9,0xbf753f7f,0x3f75bf7f,0x3e95bdc9,0x3f22bef1,0xbf463f62,0x3f46bf62,0x3f22bef1,0x3f62bf46,0xbef13f22,0x3ef1bf22,0x3f62bf46,
0x3f7fbf75,0xbdc93e95,0x3dc9be95,0x3f7fbf75,0xbf7d3f80,0xbe163d49,0xbf183f2c,0xbf4e3f3e,0xbf713f78,0xbeac3e79,0xbedb3f04,0xbf673f5c,
0xbf5c3f67,0xbf043edb,0xbe793eac,0xbf783f71,0xbf3e3f4e,0xbf2c3f18,0xbd493e16,0xbf803f7d,0x3f803f80,0xbf803f80,0x3f803f80,0xbf803f80,
0x3f803f80,0xbf803f80,0x3f803f80,0xbf803f80,0x3f803f80,0xbf803f80,0x3f803f80,0xbf803f80,0x3f803f80,0xbf803f80,0x3f803f80,0xbf803f80,
0xbf7dbf80,0x3e163d49,0xbf18bf2c,0x3f4e3f3e,0xbf71bf78,0x3eac3e79,0xbedbbf04,0x3f673f5c,0xbf5cbf67,0x3f043edb,0xbe79beac,0x3f783f71,
0xbf3ebf4e,0x3f2c3f18,0xbd49be16,0x3f803f7d,0x3f753f7f,0xbe95bdc9,0xbe95bdc9,0xbf75bf7f,0x3f463f62,0xbf22bef1,0xbf22bef1,0xbf46bf62,
0x3ef13f22,0xbf62bf46,0xbf62bf46,0xbef1bf22,0x3dc93e95,0xbf7fbf75,0xbf7fbf75,0xbdc9be95,0xbf67bf7d,0x3edb3e16,0x3f713f4e,0x3eac3f18,
0xbf04bf3e,0x3f5c3f2c,0x3f783f80,0xbe793d49,0x3d49be79,0x3f803f78,0x3f2c3f5c,0xbf3ebf04,0x3f183eac,0x3f4e3f71,0x3e163edb,0xbf7dbf67,
0x3f553f7b,0xbf0ebe48,0xbf55bf7b,0x3f0e3e48,0x3e483f0e,0xbf7bbf55,0xbe48bf0e,0x3f7b3f55,0xbf0ebe48,0xbf55bf7b,0x3f0e3e48,0x3f553f7b,
0xbf7bbf55,0xbe48bf0e,0x3f7b3f55,0x3e483f0e,0xbf3ebf78,0x3f2c3e79,0x3d493f04,0xbf80bf5c,0x3e16beac,0x3f7d3f71,0xbf4ebedb,0xbf18bf67,
0x3f673f18,0x3edb3f4e,0xbf71bf7d,0x3eacbe16,0x3f5c3f80,0xbf04bd49,0xbe79bf2c,0x3f783f3e,0x3f223f75,0xbf46be95,0x3f463e95,0x3f223f75,
0xbef13dc9,0xbf62bf7f,0x3f623f7f,0xbef13dc9,0xbf7fbf62,0x3dc9bef1,0xbdc93ef1,0xbf7fbf62,0xbe95bf46,0x3f753f22,0xbf75bf22,0xbe95bf46,
0xbf04bf71,0x3f5c3eac,0xbf78bf67,0x3e79bedb,0x3f3e3e16,0x3f2c3f7d,0x3d49bf18,0x3f803f4e,0x3f4e3f80,0xbf183d49,0x3f7d3f2c,0x3e163f3e,
0xbedb3e79,0xbf67bf78,0x3eac3f5c,0xbf71bf04,0x3ec43f6d,0xbf6dbec4,0x3ec43f6d,0xbf6dbec4,0xbf6dbec4,0xbec4bf6d,0xbf6dbec4,0xbec4bf6d,
0xbec4bf6d,0x3f6d3ec4,0xbec4bf6d,0x3f6d3ec4,0x3f6d3ec4,0x3ec43f6d,0x3f6d3ec4,0x3ec43f6d,0xbe79bf67,0x3f783edb,0x3f04beac,0x3f5c3f71,
0x3f803f18,0x3d493f4e,0x3f3e3f7d,0xbf2c3e16,0xbe163f2c,0xbf7dbf3e,0xbf4ebd49,0xbf18bf80,0xbf71bf5c,0x3eacbf04,0xbedbbf78,0x3f673e79,
0x3dc93f62,0xbf7fbef1,0xbf7fbef1,0xbdc9bf62,0xbf75bf46,0x3e95bf22,0x3e95bf22,0x3f753f46,0x3f22be95,0x3f463f75,0x3f463f75,0xbf223e95,
0x3ef13f7f,0xbf62bdc9,0xbf62bdc9,0xbef1bf7f,0x3d49bf5c,0x3f803f04,0x3f2c3f78,0xbf3e3e79,0x3f4e3f67,0xbf183edb,0xbf7dbeac,0xbe16bf71,
0xbf71be16,0xbeacbf7d,0x3edbbf18,0x3f673f4e,0x3e79bf3e,0x3f783f2c,0x3f043f80,0xbf5c3d49,0xbe483f55,0xbf7bbf0e,0x3e48bf55,0x3f7b3f0e,
0xbf0ebf7b,0x3f55be48,0x3f0e3f7b,0xbf553e48,0x3f7b3f0e,0xbe483f55,0xbf7bbf0e,0x3e48bf55,0xbf553e48,0xbf0ebf7b,0x3f55be48,0x3f0e3f7b,
0x3eacbf4e,0x3f713f18,0xbf673e16,0xbedbbf7d,0x3e793f80,0xbf78bd49,0x3f04bf2c,0x3f5c3f3e,0xbf3ebf5c,0x3f2cbf04,0x3d493f78,0xbf80be79,
0x3f7d3edb,0xbe163f67,0xbf18bf71,0x3f4ebeac,0xbef13f46,0xbf62bf22,0x3f623f22,0xbef13f46,0x3dc9bf75,0x3f7f3e95,0xbf7fbe95,0x3dc9bf75,
0x3e953f7f,0xbf753dc9,0x3f75bdc9,0x3e953f7f,0xbf22bf62,0x3f46bef1,0xbf463ef1,0xbf22bf62,0x3f18bf3e,0x3f4e3f2c,0xbe16bf80,0x3f7dbd49,
0xbedb3f5c,0xbf67bf04,0x3eac3f78,0xbf713e79,0x3e79bf71,0x3f783eac,0xbf04bf67,0x3f5cbedb,0xbd493f7d,0xbf80be16,0x3f2c3f4e,0xbf3e3f18,
0xbf353f35,0xbf35bf35,0xbf353f35,0xbf35bf35,0x3f35bf35,0x3f353f35,0x3f35bf35,0x3f353f35,0xbf353f35,0xbf35bf35,0xbf353f35,0xbf35bf35,
0x3f35bf35,0x3f353f35,0x3f35bf35,0x3f353f35,0x3f4ebf2c,0x3f183f3e,0x3f7d3d49,0xbe163f80,0xbf673f04,0xbedbbf5c,0xbf71be79,0x3eacbf78,
0x3f78beac,0x3e793f71,0x3f5c3edb,0xbf043f67,0xbf803e16,0xbd49bf7d,0xbf3ebf18,0x3f2cbf4e,0xbf623f22,0xbef1bf46,0xbef1bf46,0x3f62bf22,
0x3f7fbe95,0x3dc93f75,0x3dc93f75,0xbf7f3e95,0xbf75bdc9,0x3e95bf7f,0x3e95bf7f,0x3f753dc9,0x3f463ef1,0xbf223f62,0xbf223f62,0xbf46bef1,
0x3f71bf18,0x3eac3f4e,0xbedb3f7d,0xbf67be16,0xbf783d49,0x3e79bf80,0x3f5cbf3e,0x3f043f2c,0x3f2c3f04,0xbf3e3f5c,0xbf803e79,0x3d49bf78,
0xbe16bf67,0x3f7dbedb,0x3f4e3eac,0xbf183f71,0xbf7b3f0e,0xbe48bf55,0x3f7bbf0e,0x3e483f55,0x3f553e48,0xbf0e3f7b,0xbf55be48,0x3f0ebf7b,
0xbe48bf55,0x3f7bbf0e,0x3e483f55,0xbf7b3f0e,0xbf0e3f7b,0xbf55be48,0x3f0ebf7b,0x3f553e48,0x3f80bf04,0x3d493f5c,0xbf3ebe79,0x3f2cbf78,
0xbf18bedb,0x3f4ebf67,0xbe163f71,0xbf7d3eac,0xbeac3f7d,0xbf713e16,0x3f67bf4e,0x3edb3f18,0x3f78bf2c,0x3e793f3e,0xbf5cbd49,0x3f04bf80,
0xbf7f3ef1,0x3dc9bf62,0xbdc93f62,0xbf7f3ef1,0x3e953f22,0xbf753f46,0x3f75bf46,0x3e953f22,0x3f46bf75,0x3f223e95,0xbf22be95,0x3f46bf75,
0xbf623dc9,0x3ef1bf7f,0xbef13f7f,0xbf623dc9,0x3f78bedb,0xbe793f67,0x3f5cbf71,0x3f043eac,0x3d49bf4e,0x3f80bf18,0xbf2cbe16,0x3f3ebf7d,
0xbf7d3f3e,0xbe16bf2c,0xbf183f80,0xbf4e3d49,0x3eac3f04,0xbf713f5c,0x3f67be79,0xbedb3f78,0xbf6d3ec4,0x3ec4bf6d,0xbf6d3ec4,0x3ec4bf6d,
0xbec43f6d,0xbf6d3ec4,0xbec43f6d,0xbf6d3ec4,0x3f6dbec4,0xbec43f6d,0x3f6dbec4,0xbec43f6d,0x3ec4bf6d,0x3f6dbec4,0x3ec4bf6d,0x3f6dbec4,
0x3f5cbeac,0xbf043f71,0x3e793edb,0xbf783f67,0x3f2cbf7d,0x3f3ebe16,0x3f80bf4e,0x3d493f18,0xbf18bd49,0x3f4ebf80,0x3e16bf3e,0x3f7dbf2c,
0xbf673f78,0xbedbbe79,0xbf713f04,0x3eacbf5c,0xbf463e95,0x3f22bf75,0x3f22bf75,0x3f46be95,0xbf623f7f,0xbef1bdc9,0xbef1bdc9,0x3f62bf7f,
0x3dc93ef1,0xbf7f3f62,0xbf7f3f62,0xbdc9bef1,0x3f75bf22,0xbe953f46,0xbe953f46,0xbf753f22,0x3f2cbe79,0xbf3e3f78,0xbf803f5c,0x3d49bf04,
0x3f7dbf71,0x3e163eac,0xbf183f67,0xbf4e3edb,0x3edbbf4e,0x3f67bf18,0x3eac3e16,0xbf713f7d,0xbf043d49,0x3f5cbf80,0x3f78bf3e,0xbe793f2c,
0xbf0e3e48,0x3f55bf7b,0x3f0ebe48,0xbf553f7b,0xbf7b3f55,0x3e48bf0e,0x3f7bbf55,0xbe483f0e,0xbf553f7b,0xbf0e3e48,0x3f55bf7b,0x3f0ebe48,
0xbe483f0e,0xbf7b3f55,0x3e48bf0e,0x3f7bbf55,0x3edbbe16,0xbf673f7d,0x3eacbf18,0x3f71bf4e,0x3f5cbf2c,0xbf043f3e,0xbe79bd49,0x3f78bf80,
0x3f80bf78,0x3d493e79,0xbf3e3f04,0x3f2cbf5c,0x3f4ebf71,0x3f18beac,0xbf7d3f67,0x3e16bedb,0xbe953dc9,0x3f75bf7f,0xbf753f7f,0xbe953dc9,
0xbf223ef1,0x3f46bf62,0xbf463f62,0xbf223ef1,0xbf623f46,0x3ef1bf22,0xbef13f22,0xbf623f46,0xbf7f3f75,0x3dc9be95,0xbdc93e95,0xbf7f3f75,
0x3e16bd49,0xbf7d3f80,0x3f4ebf3e,0xbf183f2c,0x3eacbe79,0xbf713f78,0x3f67bf5c,0xbedb3f04,0x3f04bedb,0xbf5c3f67,0x3f78bf71,0xbe793eac,
0x3f2cbf18,0xbf3e3f4e,0x3f80bf7d,0xbd493e16,0x3f803f80,0xbf803f80,0x3f803f80,0xbf803f80,0x3f803f80,0xbf803f80,0x3f803f80,0xbf803f80,
0x3f803f80,0xbf803f80,0x3f803f80,0xbf803f80,0x3f803f80,0xbf803f80,0x3f803f80,0xbf803f80,0x3e163d49,0x3f7d3f80,0x3f4e3f3e,0x3f183f2c,
0x3eac3e79,0x3f713f78,0x3f673f5c,0x3edb3f04,0x3f043edb,0x3f5c3f67,0x3f783f71,0x3e793eac,0x3f2c3f18,0x3f3e3f4e,0x3f803f7d,0x3d493e16,
0xbf75bf7f,0x3e953dc9,0x3e953dc9,0x3f753f7f,0xbf46bf62,0x3f223ef1,0x3f223ef1,0x3f463f62,0xbef1bf22,0x3f623f46,0x3f623f46,0x3ef13f22,
0xbdc9be95,0x3f7f3f75,0x3f7f3f75,0x3dc93e95,0xbedbbe16,0xbf67bf7d,0xbeacbf18,0x3f713f4e,0xbf5cbf2c,0xbf04bf3e,0x3e79bd49,0x3f783f80,
0xbf80bf78,0x3d49be79,0x3f3e3f04,0x3f2c3f5c,0xbf4ebf71,0x3f183eac,0x3f7d3f67,0x3e163edb,0x3f553f7b,0xbf0ebe48,0xbf55bf7b,0x3f0e3e48,
0x3e483f0e,0xbf7bbf55,0xbe48bf0e,0x3f7b3f55,0xbf0ebe48,0xbf55bf7b,0x3f0e3e48,0x3f553f7b,0xbf7bbf55,0xbe48bf0e,0x3f7b3f55,0x3e483f0e,
0x3f2c3e79,0x3f3e3f78,0xbf80bf5c,0xbd49bf04,0x3f7d3f71,0xbe163eac,0xbf18bf67,0x3f4e3edb,0x3edb3f4e,0xbf67bf18,0x3eacbe16,0x3f713f7d,
0xbf04bd49,0xbf5cbf80,0x3f783f3e,0x3e793f2c,0xbf22bf75,0x3f463e95,0xbf46be95,0xbf22bf75,0x3ef1bdc9,0x3f623f7f,0xbf62bf7f,0x3ef1bdc9,
0x3f7f3f62,0xbdc93ef1,0x3dc9bef1,0x3f7f3f62,0x3e953f46,0xbf75bf22,0x3f753f22,0x3e953f46,0xbf5cbeac,0xbf04bf71,0xbe793edb,0xbf78bf67,
0xbf2cbf7d,0x3f3e3e16,0xbf80bf4e,0x3d49bf18,0x3f18bd49,0x3f4e3f80,0xbe16bf3e,0x3f7d3f2c,0x3f673f78,0xbedb3e79,0x3f713f04,0x3eac3f5c,
0x3ec43f6d,0xbf6dbec4,0x3ec43f6d,0xbf6dbec4,0xbf6dbec4,0xbec4bf6d,0xbf6dbec4,0xbec4bf6d,0xbec4bf6d,0x3f6d3ec4,0xbec4bf6d,0x3f6d3ec4,
0x3f6d3ec4,0x3ec43f6d,0x3f6d3ec4,0x3ec43f6d,0x3f783edb,0x3e793f67,0x3f5c3f71,0xbf043eac,0x3d493f4e,0xbf80bf18,0xbf2c3e16,0xbf3ebf7d,
0xbf7dbf3e,0x3e16bf2c,0xbf18bf80,0x3f4e3d49,0x3eacbf04,0x3f713f5c,0x3f673e79,0x3edb3f78,0xbdc9bf62,0x3f7f3ef1,0x3f7f3ef1,0x3dc93f62,
0x3f753f46,0xbe953f22,0xbe953f22,0xbf75bf46,0xbf223e95,0xbf46bf75,0xbf46bf75,0x3f22be95,0xbef1bf7f,0x3f623dc9,0x3f623dc9,0x3ef13f7f,
0xbf80bf04,0x3d49bf5c,0x3f3ebe79,0x3f2c3f78,0x3f18bedb,0x3f4e3f67,0x3e163f71,0xbf7dbeac,0x3eac3f7d,0xbf71be16,0xbf67bf4e,0x3edbbf18,
0xbf78bf2c,0x3e79bf3e,0x3f5cbd49,0x3f043f80,0xbe483f55,0xbf7bbf0e,0x3e48bf55,0x3f7b3f0e,0xbf0ebf7b,0x3f55be48,0x3f0e3f7b,0xbf553e48,
0x3f7b3f0e,0xbe483f55,0xbf7bbf0e,0x3e48bf55,0xbf553e48,0xbf0ebf7b,0x3f55be48,0x3f0e3f7b,0x3f713f18,0xbeac3f4e,0xbedbbf7d,0x3f67be16,
0xbf78bd49,0xbe79bf80,0x3f5c3f3e,0xbf043f2c,0x3f2cbf04,0x3f3e3f5c,0xbf80be79,0xbd49bf78,0xbe163f67,0xbf7dbedb,0x3f4ebeac,0x3f183f71,
0x3ef1bf46,0x3f623f22,0xbf62bf22,0x3ef1bf46,0xbdc93f75,0xbf7fbe95,0x3f7f3e95,0xbdc93f75,0xbe95bf7f,0x3f75bdc9,0xbf753dc9,0xbe95bf7f,
0x3f223f62,0xbf463ef1,0x3f46bef1,0x3f223f62,0xbf4ebf2c,0x3f18bf3e,0xbf7d3d49,0xbe16bf80,0x3f673f04,0xbedb3f5c,0x3f71be79,0x3eac3f78,
0xbf78beac,0x3e79bf71,0xbf5c3edb,0xbf04bf67,0x3f803e16,0xbd493f7d,0x3f3ebf18,0x3f2c3f4e,0xbf353f35,0xbf35bf35,0xbf353f35,0xbf35bf35,
0x3f35bf35,0x3f353f35,0x3f35bf35,0x3f353f35,0xbf353f35,0xbf35bf35,0xbf353f35,0xbf35bf35,0x3f35bf35,0x3f353f35,0x3f35bf35,0x3f353f35,
0x3f183f3e,0xbf4e3f2c,0xbe163f80,0xbf7dbd49,0xbedbbf5c,0x3f67bf04,0x3eacbf78,0x3f713e79,0x3e793f71,0xbf783eac,0xbf043f67,0xbf5cbedb,
0xbd49bf7d,0x3f80be16,0x3f2cbf4e,0x3f3e3f18,0x3f62bf22,0x3ef13f46,0x3ef13f46,0xbf623f22,0xbf7f3e95,0xbdc9bf75,0xbdc9bf75,0x3f7fbe95,
0x3f753dc9,0xbe953f7f,0xbe953f7f,0xbf75bdc9,0xbf46bef1,0x3f22bf62,0x3f22bf62,0x3f463ef1,0xbeacbf4e,0x3f71bf18,0x3f673e16,0xbedb3f7d,
0xbe793f80,0xbf783d49,0xbf04bf2c,0x3f5cbf3e,0x3f3ebf5c,0x3f2c3f04,0xbd493f78,0xbf803e79,0xbf7d3edb,0xbe16bf67,0x3f18bf71,0x3f4e3eac,
0xbf7b3f0e,0xbe48bf55,0x3f7bbf0e,0x3e483f55,0x3f553e48,0xbf0e3f7b,0xbf55be48,0x3f0ebf7b,0xbe48bf55,0x3f7bbf0e,0x3e483f55,0xbf7b3f0e,
0xbf0e3f7b,0xbf55be48,0x3f0ebf7b,0x3f553e48,0x3d493f5c,0xbf803f04,0x3f2cbf78,0x3f3e3e79,0x3f4ebf67,0x3f183edb,0xbf7d3eac,0x3e16bf71,
0xbf713e16,0x3eacbf7d,0x3edb3f18,0xbf673f4e,0x3e793f3e,0xbf783f2c,0x3f04bf80,0x3f5c3d49,0x3f7fbef1,0xbdc93f62,0x3dc9bf62,0x3f7fbef1,
0xbe95bf22,0x3f75bf46,0xbf753f46,0xbe95bf22,0xbf463f75,0xbf22be95,0x3f223e95,0xbf463f75,0x3f62bdc9,0xbef13f7f,0x3ef1bf7f,0x3f62bdc9,
0x3e79bf67,0x3f78bedb,0xbf04beac,0x3f5cbf71,0xbf803f18,0x3d49bf4e,0xbf3e3f7d,0xbf2cbe16,0x3e163f2c,0xbf7d3f3e,0x3f4ebd49,0xbf183f80,
0x3f71bf5c,0x3eac3f04,0x3edbbf78,0x3f67be79,0xbf6d3ec4,0x3ec4bf6d,0xbf6d3ec4,0x3ec4bf6d,0xbec43f6d,0xbf6d3ec4,0xbec43f6d,0xbf6d3ec4,
0x3f6dbec4,0xbec43f6d,0x3f6dbec4,0xbec43f6d,0x3ec4bf6d,0x3f6dbec4,0x3ec4bf6d,0x3f6dbec4,0xbf043f71,0xbf5c3eac,0xbf783f67,0xbe79bedb,
0x3f3ebe16,0xbf2c3f7d,0x3d493f18,0xbf803f4e,0x3f4ebf80,0x3f183d49,0x3f7dbf2c,0xbe163f3e,0xbedbbe79,0x3f67bf78,0x3eacbf5c,0x3f71bf04,
0x3f46be95,0xbf223f75,0xbf223f75,0xbf463e95,0x3f62bf7f,0x3ef13dc9,0x3ef13dc9,0xbf623f7f,0xbdc9bef1,0x3f7fbf62,0x3f7fbf62,0x3dc93ef1,
0xbf753f22,0x3e95bf46,0x3e95bf46,0x3f75bf22,0x3f3ebf78,0x3f2cbe79,0xbd493f04,0xbf803f5c,0xbe16beac,0x3f7dbf71,0x3f4ebedb,0xbf183f67,
0xbf673f18,0x3edbbf4e,0x3f71bf7d,0x3eac3e16,0xbf5c3f80,0xbf043d49,0x3e79bf2c,0x3f78bf3e,0xbf0e3e48,0x3f55bf7b,0x3f0ebe48,0xbf553f7b,
0xbf7b3f55,0x3e48bf0e,0x3f7bbf55,0xbe483f0e,0xbf553f7b,0xbf0e3e48,0x3f55bf7b,0x3f0ebe48,0xbe483f0e,0xbf7b3f55,0x3e48bf0e,0x3f7bbf55,
0xbf673f7d,0xbedb3e16,0x3f71bf4e,0xbeac3f18,0xbf043f3e,0xbf5c3f2c,0x3f78bf80,0x3e793d49,0x3d493e79,0xbf803f78,0x3f2cbf5c,0x3f3ebf04,
0x3f18beac,0xbf4e3f71,0x3e16bedb,0x3f7dbf67,0x3e95bdc9,0xbf753f7f,0x3f75bf7f,0x3e95bdc9,0x3f22bef1,0xbf463f62,0x3f46bf62,0x3f22bef1,
0x3f62bf46,0xbef13f22,0x3ef1bf22,0x3f62bf46,0x3f7fbf75,0xbdc93e95,0x3dc9be95,0x3f7fbf75,0x3f7dbf80,0x3e16bd49,0x3f18bf2c,0x3f4ebf3e,
0x3f71bf78,0x3eacbe79,0x3edbbf04,0x3f67bf5c,0x3f5cbf67,0x3f04bedb,0x3e79beac,0x3f78bf71,0x3f3ebf4e,0x3f2cbf18,0x3d49be16,0x3f80bf7d,
0x3f803f80,0xbf353f35,0x3f803f80,0xbf353f35,0x3f803f80,0xbf353f35,0x3f803f80,0xbf353f35,0x3f803f80,0xbf353f35,0x3f803f80,0xbf353f35,
0x3f803f80,0xbf353f35,0x3f803f80,0xbf353f35,0x3f7c3f7f,0xbe2fbd97,0x3f133f27,0xbf51bf42,0x3f6f3f77,0xbeb8be89,0x3ecf3efc,0xbf6abf5f,
0x3f583f65,0xbf09bee6,0x3e603ea1,0xbf7abf73,0x3f393f4a,0xbf31bf1d,0x3cc93dfb,0xbf80bf7e,0x3f713f7d,0xbeacbe16,0xbeacbe16,0xbf71bf7d,
0x3f3e3f5c,0xbf2cbf04,0xbf2cbf04,0xbf3ebf5c,0x3edb3f18,0xbf67bf4e,0xbf67bf4e,0xbedbbf18,0x3d493e79,0xbf80bf78,0xbf80bf78,0xbd49be79,
0x3f5f3f7a,0xbefcbe60,0xbf77bf58,0xbe89bf09,0x3ee63f31,0xbf65bf39,0xbf73bf80,0x3ea13cc9,0xbdfb3e2f,0xbf7ebf7c,0xbf1dbf51,0x3f4a3f13,
0xbf27becf,0xbf42bf6a,0xbd97beb8,0x3f7f3f6f,0x3f463f75,0xbf22be95,0xbf46bf75,0x3f223e95,0x3dc93ef1,0xbf7fbf62,0xbdc9bef1,0x3f7f3f62,
0xbf22be95,0xbf46bf75,0x3f223e95,0x3f463f75,0xbf7fbf62,0xbdc9bef1,0x3f7f3f62,0x3dc93ef1,0x3f273f6f,0xbf42beb8,0x3d97becf,0x3f7f3f6a,
0xbe893e60,0xbf77bf7a,0x3f5f3f09,0x3efc3f58,0xbf73bf31,0xbea1bf39,0x3f653f80,0xbee63cc9,0xbf4abf7c,0x3f1d3e2f,0x3dfb3f13,0xbf7ebf51,
0x3f043f67,0xbf5cbedb,0x3f5c3edb,0x3f043f67,0xbf18bd49,0xbf4ebf80,0x3f4e3f80,0xbf18bd49,0xbf78bf71,0x3e79beac,0xbe793eac,0xbf78bf71,
0xbe16bf2c,0x3f7d3f3e,0xbf7dbf3e,0xbe16bf2c,0x3eb83f5f,0xbf6fbefc,0x3f6a3f77,0xbecf3e89,0xbf58bea1,0xbf09bf73,0xbe603ee6,0xbf7abf65,
0xbf31bf7e,0x3f393dfb,0xbf80bf4a,0x3cc9bf1d,0x3f13bd97,0x3f513f7f,0xbe2fbf42,0x3f7c3f27,0x3e483f55,0xbf7bbf0e,0x3e483f55,0xbf7bbf0e,
0xbf7bbf0e,0xbe48bf55,0xbf7bbf0e,0xbe48bf55,0xbe48bf55,0x3f7b3f0e,0xbe48bf55,0x3f7b3f0e,0x3f7b3f0e,0x3e483f55,0x3f7b3f0e,0x3e483f55,
0x3cc93f4a,0xbf80bf1d,0xbf313dfb,0xbf39bf7e,0xbf7cbf42,0x3e2fbf27,0xbf13bf7f,0x3f513d97,0x3eb8befc,0x3f6f3f5f,0x3f6a3e89,0x3ecf3f77,
0x3f583f73,0xbf093ea1,0x3e603f65,0xbf7abee6,0xbe163f3e,0xbf7dbf2c,0xbf7dbf2c,0x3e16bf3e,0xbf5cbf67,0x3f04bedb,0x3f04bedb,0x3f5c3f67,
0x3f4ebd49,0x3f183f80,0x3f183f80,0xbf4e3d49,0x3e793f71,0xbf78beac,0xbf78beac,0xbe79bf71,0xbea13f31,0xbf73bf39,0xbee6bf80,0x3f653cc9,
0xbf1dbf7c,0x3f4abe2f,0x3f7e3f13,0xbdfb3f51,0x3f7f3ecf,0x3d973f6a,0xbf273eb8,0xbf42bf6f,0xbefc3f09,0xbf5fbf58,0xbe89bf7a,0x3f773e60,
0xbef13f22,0xbf62bf46,0x3ef1bf22,0x3f623f46,0xbe95bf7f,0x3f753dc9,0x3e953f7f,0xbf75bdc9,0x3f623f46,0xbef13f22,0xbf62bf46,0x3ef1bf22,
0xbf75bdc9,0xbe95bf7f,0x3f753dc9,0x3e953f7f,0xbf1d3f13,0xbf4abf51,0x3f7e3e2f,0x3dfb3f7c,0x3d97bf6f,0x3f7f3eb8,0xbf423ecf,0xbf27bf6a,
0x3efc3f7a,0xbf5f3e60,0x3e89bf58,0x3f773f09,0xbf65bf31,0x3ee6bf39,0x3ea13f80,0xbf733cc9,0xbf3e3f04,0xbf2cbf5c,0x3f2c3f5c,0xbf3e3f04,
0x3edbbf4e,0x3f673f18,0xbf67bf18,0x3edbbf4e,0xbd493f78,0xbf80be79,0x3f803e79,0xbd493f78,0xbeacbf7d,0x3f71be16,0xbf713e16,0xbeacbf7d,
0xbf583ee6,0xbf09bf65,0xbe603f73,0xbf7abea1,0x3f39bf1d,0x3f313f4a,0x3cc9bf7e,0x3f803dfb,0xbf133f42,0xbf51bf27,0x3e2f3f7f,0xbf7c3d97,
0x3ecfbf5f,0x3f6a3efc,0xbeb8bf77,0x3f6fbe89,0xbf6d3ec4,0xbec4bf6d,0xbf6d3ec4,0xbec4bf6d,0x3f6dbec4,0x3ec43f6d,0x3f6dbec4,0x3ec43f6d,
0xbf6d3ec4,0xbec4bf6d,0xbf6d3ec4,0xbec4bf6d,0x3f6dbec4,0x3ec43f6d,0x3f6dbec4,0x3ec43f6d,0xbf7a3ea1,0xbe60bf73,0xbf58bee6,0x3f09bf65,
0x3f80bdfb,0x3cc93f7e,0x3f393f1d,0xbf313f4a,0xbf7cbd97,0x3e2fbf7f,0xbf13bf42,0x3f51bf27,0x3f6f3e89,0xbeb83f77,0x3ecf3f5f,0xbf6a3efc,
0xbf803e79,0xbd49bf78,0xbd49bf78,0x3f80be79,0x3f713e16,0xbeac3f7d,0xbeac3f7d,0xbf71be16,0xbf3ebf04,0x3f2cbf5c,0x3f2cbf5c,0x3f3e3f04,
0x3edb3f4e,0xbf673f18,0xbf673f18,0xbedbbf4e,0xbf7e3e2f,0x3dfbbf7c,0x3f4abf51,0x3f1d3f13,0x3f423ecf,0xbf273f6a,0xbf7f3eb8,0xbd97bf6f,
0xbe89bf58,0x3f77bf09,0x3f5f3e60,0xbefc3f7a,0xbea13f80,0xbf73bcc9,0xbee6bf39,0x3f65bf31,0xbf753dc9,0x3e95bf7f,0x3f75bdc9,0xbe953f7f,
0x3ef13f22,0xbf623f46,0xbef1bf22,0x3f62bf46,0x3e95bf7f,0x3f75bdc9,0xbe953f7f,0xbf753dc9,0xbf623f46,0xbef1bf22,0x3f62bf46,0x3ef13f22,
0xbf653cc9,0x3ee6bf80,0x3ea13f31,0xbf733f39,0x3dfb3f51,0xbf7e3f13,0x3f1dbf7c,0x3f4a3e2f,0x3f42bf6f,0x3f273eb8,0xbf7f3ecf,0x3d97bf6a,
0xbf773e60,0x3e89bf7a,0x3efc3f09,0xbf5f3f58,0xbf4ebd49,0x3f18bf80,0xbf183f80,0xbf4ebd49,0xbe793f71,0xbf783eac,0x3f78beac,0xbe793f71,
0x3f7dbf2c,0x3e163f3e,0xbe16bf3e,0x3f7dbf2c,0xbf04bedb,0x3f5cbf67,0xbf5c3f67,0xbf04bedb,0xbf31bdfb,0x3f39bf7e,0xbf803f1d,0x3cc9bf4a,
0xbf133f7f,0xbf513d97,0x3e2f3f27,0xbf7c3f42,0x3f6abe89,0xbecf3f77,0x3f6fbf5f,0x3eb83efc,0x3e60bf65,0x3f7abee6,0xbf09bea1,0x3f58bf73,
0xbf0ebe48,0x3f55bf7b,0xbf0ebe48,0x3f55bf7b,0xbf553f7b,0xbf0ebe48,0xbf553f7b,0xbf0ebe48,0x3f0e3e48,0xbf553f7b,0x3f0e3e48,0xbf553f7b,
0x3f55bf7b,0x3f0e3e48,0x3f55bf7b,0x3f0e3e48,0xbecfbe89,0x3f6abf77,0x3eb8bf5f,0x3f6fbefc,0xbf7a3f65,0xbe60bee6,0xbf583ea1,0x3f09bf73,
0x3cc93f1d,0xbf803f4a,0xbf313f7e,0xbf393dfb,0x3f7cbf27,0xbe2f3f42,0x3f133d97,0xbf513f7f,0xbe79beac,0x3f78bf71,0x3f78bf71,0x3e793eac,
0xbf7d3f3e,0x3e16bf2c,0x3e16bf2c,0x3f7dbf3e,0xbf043f67,0xbf5c3edb,0xbf5c3edb,0x3f04bf67,0x3f18bd49,0xbf4e3f80,0xbf4e3f80,0xbf183d49,
0xbd97becf,0x3f7fbf6a,0x3f42beb8,0xbf273f6f,0xbf5f3f09,0x3efcbf58,0x3f77bf7a,0x3e893e60,0xbf653f80,0xbee6bcc9,0x3ea1bf39,0x3f73bf31,
0xbdfb3f13,0xbf7e3f51,0xbf1d3e2f,0x3f4abf7c,0x3dc9bef1,0x3f7fbf62,0xbdc93ef1,0xbf7f3f62,0xbf223e95,0x3f46bf75,0x3f22be95,0xbf463f75,
0xbf7f3f62,0x3dc9bef1,0x3f7fbf62,0xbdc93ef1,0xbf463f75,0xbf223e95,0x3f46bf75,0x3f22be95,0x3e89bf09,0x3f77bf58,0xbf5f3f7a,0xbefc3e60,
0xbea13cc9,0x3f73bf80,0xbee63f31,0xbf653f39,0xbf4a3f13,0x3f1dbf51,0x3dfb3e2f,0xbf7e3f7c,0xbf7f3f6f,0x3d97beb8,0x3f27becf,0xbf423f6a,
0x3edbbf18,0x3f67bf4e,0xbf673f4e,0x3edbbf18,0x3d49be79,0x3f80bf78,0xbf803f78,0x3d49be79,0xbeac3e16,0x3f71bf7d,0xbf713f7d,0xbeac3e16,
0xbf2c3f04,0x3f3ebf5c,0xbf3e3f5c,0xbf2c3f04,0x3f13bf27,0x3f51bf42,0xbe2f3d97,0x3f7cbf7f,0x3ecfbefc,0x3f6abf5f,0xbeb83e89,0x3f6fbf77,
0x3e60bea1,0x3f7abf73,0xbf093ee6,0x3f58bf65,0x3cc9bdfb,0x3f80bf7e,0xbf313f1d,0x3f39bf4a,0x3f803f80,0xbf353f35,0x3f803f80,0xbf353f35,
0x3f803f80,0xbf353f35,0x3f803f80,0xbf353f35,0x3f803f80,0xbf353f35,0x3f803f80,0xbf353f35,0x3f803f80,0xbf353f35,0x3f803f80,0xbf353f35,
0xbe2fbd97,0xbf7cbf7f,0xbf51bf42,0xbf13bf27,0xbeb8be89,0xbf6fbf77,0xbf6abf5f,0xbecfbefc,0xbf09bee6,0xbf58bf65,0xbf7abf73,0xbe60bea1,
0xbf31bf1d,0xbf39bf4a,0xbf80bf7e,0xbcc9bdfb,0xbf71bf7d,0x3eac3e16,0x3eac3e16,0x3f713f7d,0xbf3ebf5c,0x3f2c3f04,0x3f2c3f04,0x3f3e3f5c,
0xbedbbf18,0x3f673f4e,0x3f673f4e,0x3edb3f18,0xbd49be79,0x3f803f78,0x3f803f78,0x3d493e79,0x3efc3e60,0x3f5f3f7a,0x3e893f09,0xbf77bf58,
0x3f653f39,0x3ee63f31,0xbea1bcc9,0xbf73bf80,0x3f7e3f7c,0xbdfb3e2f,0xbf4abf13,0xbf1dbf51,0x3f423f6a,0xbf27becf,0xbf7fbf6f,0xbd97beb8,
0x3f463f75,0xbf22be95,0xbf46bf75,0x3f223e95,0x3dc93ef1,0xbf7fbf62,0xbdc9bef1,0x3f7f3f62,0xbf22be95,0xbf46bf75,0x3f223e95,0x3f463f75,
0xbf7fbf62,0xbdc9bef1,0x3f7f3f62,0x3dc93ef1,0xbf42beb8,0xbf27bf6f,0x3f7f3f6a,0xbd973ecf,0xbf77bf7a,0x3e89be60,0x3efc3f58,0xbf5fbf09,
0xbea1bf39,0x3f733f31,0xbee63cc9,0xbf65bf80,0x3f1d3e2f,0x3f4a3f7c,0xbf7ebf51,0xbdfbbf13,0xbf04bf67,0x3f5c3edb,0xbf5cbedb,0xbf04bf67,
0x3f183d49,0x3f4e3f80,0xbf4ebf80,0x3f183d49,0x3f783f71,0xbe793eac,0x3e79beac,0x3f783f71,0x3e163f2c,0xbf7dbf3e,0x3f7d3f3e,0x3e163f2c,
0x3f6f3efc,0x3eb83f5f,0x3ecfbe89,0x3f6a3f77,0x3f093f73,0xbf58bea1,0x3f7a3f65,0xbe603ee6,0xbf39bdfb,0xbf31bf7e,0xbcc93f1d,0xbf80bf4a,
0xbf51bf7f,0x3f13bd97,0xbf7cbf27,0xbe2fbf42,0x3e483f55,0xbf7bbf0e,0x3e483f55,0xbf7bbf0e,0xbf7bbf0e,0xbe48bf55,0xbf7bbf0e,0xbe48bf55,
0xbe48bf55,0x3f7b3f0e,0xbe48bf55,0x3f7b3f0e,0x3f7b3f0e,0x3e483f55,0x3f7b3f0e,0x3e483f55,0xbf80bf1d,0xbcc9bf4a,0xbf39bf7e,0x3f31bdfb,
0x3e2fbf27,0x3f7c3f42,0x3f513d97,0x3f133f7f,0x3f6f3f5f,0xbeb83efc,0x3ecf3f77,0xbf6abe89,0xbf093ea1,0xbf58bf73,0xbf7abee6,0xbe60bf65,
0x3e16bf3e,0x3f7d3f2c,0x3f7d3f2c,0xbe163f3e,0x3f5c3f67,0xbf043edb,0xbf043edb,0xbf5cbf67,0xbf4e3d49,0xbf18bf80,0xbf18bf80,0x3f4ebd49,
0xbe79bf71,0x3f783eac,0x3f783eac,0x3e793f71,0x3f733f39,0xbea13f31,0xbf65bcc9,0xbee6bf80,0xbf4a3e2f,0xbf1dbf7c,0x3dfbbf51,0x3f7e3f13,
0xbd97bf6a,0x3f7f3ecf,0x3f423f6f,0xbf273eb8,0x3f5f3f58,0xbefc3f09,0xbf77be60,0xbe89bf7a,0xbef13f22,0xbf62bf46,0x3ef1bf22,0x3f623f46,
0xbe95bf7f,0x3f753dc9,0x3e953f7f,0xbf75bdc9,0x3f623f46,0xbef13f22,0xbf62bf46,0x3ef1bf22,0xbf75bdc9,0xbe95bf7f,0x3f753dc9,0x3e953f7f,
0xbf4abf51,0x3f1dbf13,0x3dfb3f7c,0xbf7ebe2f,0x3f7f3eb8,0xbd973f6f,0xbf27bf6a,0x3f42becf,0xbf5f3e60,0xbefcbf7a,0x3f773f09,0xbe893f58,
0x3ee6bf39,0x3f653f31,0xbf733cc9,0xbea1bf80,0x3f3ebf04,0x3f2c3f5c,0xbf2cbf5c,0x3f3ebf04,0xbedb3f4e,0xbf67bf18,0x3f673f18,0xbedb3f4e,
0x3d49bf78,0x3f803e79,0xbf80be79,0x3d49bf78,0x3eac3f7d,0xbf713e16,0x3f71be16,0x3eac3f7d,0x3f093f65,0xbf583ee6,0x3f7a3ea1,0xbe603f73,
0xbf31bf4a,0x3f39bf1d,0xbf80bdfb,0x3cc9bf7e,0x3f513f27,0xbf133f42,0x3f7cbd97,0x3e2f3f7f,0xbf6abefc,0x3ecfbf5f,0xbf6f3e89,0xbeb8bf77,
0xbf6d3ec4,0xbec4bf6d,0xbf6d3ec4,0xbec4bf6d,0x3f6dbec4,0x3ec43f6d,0x3f6dbec4,0x3ec43f6d,0xbf6d3ec4,0xbec4bf6d,0xbf6d3ec4,0xbec4bf6d,
0x3f6dbec4,0x3ec43f6d,0x3f6dbec4,0x3ec43f6d,0xbe60bf73,0x3f7abea1,0x3f09bf65,0x3f583ee6,0x3cc93f7e,0xbf803dfb,0xbf313f4a,0xbf39bf1d,
0x3e2fbf7f,0x3f7c3d97,0x3f51bf27,0x3f133f42,0xbeb83f77,0xbf6fbe89,0xbf6a3efc,0xbecfbf5f,0x3f80be79,0x3d493f78,0x3d493f78,0xbf803e79,
0xbf71be16,0x3eacbf7d,0x3eacbf7d,0x3f713e16,0x3f3e3f04,0xbf2c3f5c,0xbf2c3f5c,0xbf3ebf04,0xbedbbf4e,0x3f67bf18,0x3f67bf18,0x3edb3f4e,
0xbdfb3f7c,0xbf7e3e2f,0xbf1dbf13,0x3f4abf51,0x3f27bf6a,0x3f423ecf,0x3d973f6f,0xbf7f3eb8,0xbf773f09,0xbe89bf58,0x3efcbf7a,0x3f5f3e60,
0x3f733cc9,0xbea13f80,0xbf653f31,0xbee6bf39,0xbf753dc9,0x3e95bf7f,0x3f75bdc9,0xbe953f7f,0x3ef13f22,0xbf623f46,0xbef1bf22,0x3f62bf46,
0x3e95bf7f,0x3f75bdc9,0xbe953f7f,0xbf753dc9,0xbf623f46,0xbef1bf22,0x3f62bf46,0x3ef13f22,0x3ee6bf80,0x3f65bcc9,0xbf733f39,0xbea1bf31,
0xbf7e3f13,0xbdfbbf51,0x3f4a3e2f,0xbf1d3f7c,0x3f273eb8,0xbf423f6f,0x3d97bf6a,0x3f7fbecf,0x3e89bf7a,0x3f77be60,0xbf5f3f58,0xbefcbf09,
0x3f4e3d49,0xbf183f80,0x3f18bf80,0x3f4e3d49,0x3e79bf71,0x3f78beac,0xbf783eac,0x3e79bf71,0xbf7d3f2c,0xbe16bf3e,0x3e163f3e,0xbf7d3f2c,
0x3f043edb,0xbf5c3f67,0x3f5cbf67,0x3f043edb,0xbf393f7e,0xbf31bdfb,0xbcc93f4a,0xbf803f1d,0x3f51bd97,0xbf133f7f,0x3f7cbf42,0x3e2f3f27,
0x3ecfbf77,0x3f6abe89,0xbeb8befc,0x3f6fbf5f,0xbf7a3ee6,0x3e60bf65,0xbf583f73,0xbf09bea1,0xbf0ebe48,0x3f55bf7b,0xbf0ebe48,0x3f55bf7b,
0xbf553f7b,0xbf0ebe48,0xbf553f7b,0xbf0ebe48,0x3f0e3e48,0xbf553f7b,0x3f0e3e48,0xbf553f7b,0x3f55bf7b,0x3f0e3e48,0x3f55bf7b,0x3f0e3e48,
0x3f6abf77,0x3ecf3e89,0x3f6fbefc,0xbeb83f5f,0xbe60bee6,0x3f7abf65,0x3f09bf73,0x3f58bea1,0xbf803f4a,0xbcc9bf1d,0xbf393dfb,0x3f31bf7e,
0xbe2f3f42,0xbf7c3f27,0xbf513f7f,0xbf13bd97,0x3e793eac,0xbf783f71,0xbf783f71,0xbe79beac,0x3f7dbf3e,0xbe163f2c,0xbe163f2c,0xbf7d3f3e,
0x3f04bf67,0x3f5cbedb,0x3f5cbedb,0xbf043f67,0xbf183d49,0x3f4ebf80,0x3f4ebf80,0x3f18bd49,0xbf7f3f6a,0xbd97becf,0x3f27bf6f,0x3f42beb8,
0xbefc3f58,0xbf5f3f09,0xbe89be60,0x3f77bf7a,0x3ee63cc9,0xbf653f80,0xbf733f31,0x3ea1bf39,0x3f7ebf51,0xbdfb3f13,0xbf4a3f7c,0xbf1d3e2f,
0x3dc9bef1,0x3f7fbf62,0xbdc93ef1,0xbf7f3f62,0xbf223e95,0x3f46bf75,0x3f22be95,0xbf463f75,0xbf7f3f62,0x3dc9bef1,0x3f7fbf62,0xbdc93ef1,
0xbf463f75,0xbf223e95,0x3f46bf75,0x3f22be95,0x3f77bf58,0xbe893f09,0xbefc3e60,0x3f5fbf7a,0x3f73bf80,0x3ea1bcc9,0xbf653f39,0x3ee6bf31,
0x3f1dbf51,0x3f4abf13,0xbf7e3f7c,0xbdfbbe2f,0x3d97beb8,0x3f7fbf6f,0xbf423f6a,0xbf273ecf,0xbedb3f18,0xbf673f4e,0x3f67bf4e,0xbedb3f18,
0xbd493e79,0xbf803f78,0x3f80bf78,0xbd493e79,0x3eacbe16,0xbf713f7d,0x3f71bf7d,0x3eacbe16,0x3f2cbf04,0xbf3e3f5c,0x3f3ebf5c,0x3f2cbf04,
0xbf513f42,0x3f13bf27,0xbf7c3f7f,0xbe2f3d97,0xbf6a3f5f,0x3ecfbefc,0xbf6f3f77,0xbeb83e89,0xbf7a3f73,0x3e60bea1,0xbf583f65,0xbf093ee6,
0xbf803f7e,0x3cc9bdfb,0xbf393f4a,0xbf313f1d,0x3f803f80,0xbf353f35,0x3f803f80,0xbf353f35,0x3f803f80,0xbf353f35,0x3f803f80,0xbf353f35,
0x3f803f80,0xbf353f35,0x3f803f80,0xbf353f35,0x3f803f80,0xbf353f35,0x3f803f80,0xbf353f35,0xbf7cbf7f,0x3e2f3d97,0xbf13bf27,0x3f513f42,
0xbf6fbf77,0x3eb83e89,0xbecfbefc,0x3f6a3f5f,0xbf58bf65,0x3f093ee6,0xbe60bea1,0x3f7a3f73,0xbf39bf4a,0x3f313f1d,0xbcc9bdfb,0x3f803f7e,
0x3f713f7d,0xbeacbe16,0xbeacbe16,0xbf71bf7d,0x3f3e3f5c,0xbf2cbf04,0xbf2cbf04,0xbf3ebf5c,0x3edb3f18,0xbf67bf4e,0xbf67bf4e,0xbedbbf18,
0x3d493e79,0xbf80bf78,0xbf80bf78,0xbd49be79,0xbf5fbf7a,0x3efc3e60,0x3f773f58,0x3e893f09,0xbee6bf31,0x3f653f39,0x3f733f80,0xbea1bcc9,
0x3dfbbe2f,0x3f7e3f7c,0x3f1d3f51,0xbf4abf13,0x3f273ecf,0x3f423f6a,0x3d973eb8,0xbf7fbf6f,0x3f463f75,0xbf22be95,0xbf46bf75,0x3f223e95,
0x3dc93ef1,0xbf7fbf62,0xbdc9bef1,0x3f7f3f62,0xbf22be95,0xbf46bf75,0x3f223e95,0x3f463f75,0xbf7fbf62,0xbdc9bef1,0x3f7f3f62,0x3dc93ef1,
0xbf27bf6f,0x3f423eb8,0xbd973ecf,0xbf7fbf6a,0x3e89be60,0x3f773f7a,0xbf5fbf09,0xbefcbf58,0x3f733f31,0x3ea13f39,0xbf65bf80,0x3ee6bcc9,
0x3f4a3f7c,0xbf1dbe2f,0xbdfbbf13,0x3f7e3f51,0x3f043f67,0xbf5cbedb,0x3f5c3edb,0x3f043f67,0xbf18bd49,0xbf4ebf80,0x3f4e3f80,0xbf18bd49,
0xbf78bf71,0x3e79beac,0xbe793eac,0xbf78bf71,0xbe16bf2c,0x3f7d3f3e,0xbf7dbf3e,0xbe16bf2c,0xbeb8bf5f,0x3f6f3efc,0xbf6abf77,0x3ecfbe89,
0x3f583ea1,0x3f093f73,0x3e60bee6,0x3f7a3f65,0x3f313f7e,0xbf39bdfb,0x3f803f4a,0xbcc93f1d,0xbf133d97,0xbf51bf7f,0x3e2f3f42,0xbf7cbf27,
0x3e483f55,0xbf7bbf0e,0x3e483f55,0xbf7bbf0e,0xbf7bbf0e,0xbe48bf55,0xbf7bbf0e,0xbe48bf55,0xbe48bf55,0x3f7b3f0e,0xbe48bf55,0x3f7b3f0e,
0x3f7b3f0e,0x3e483f55,0x3f7b3f0e,0x3e483f55,0xbcc9bf4a,0x3f803f1d,0x3f31bdfb,0x3f393f7e,0x3f7c3f42,0xbe2f3f27,0x3f133f7f,0xbf51bd97,
0xbeb83efc,0xbf6fbf5f,0xbf6abe89,0xbecfbf77,0xbf58bf73,0x3f09bea1,0xbe60bf65,0x3f7a3ee6,0xbe163f3e,0xbf7dbf2c,0xbf7dbf2c,0x3e16bf3e,
0xbf5cbf67,0x3f04bedb,0x3f04bedb,0x3f5c3f67,0x3f4ebd49,0x3f183f80,0x3f183f80,0xbf4e3d49,0x3e793f71,0xbf78beac,0xbf78beac,0xbe79bf71,
0x3ea1bf31,0x3f733f39,0x3ee63f80,0xbf65bcc9,0x3f1d3f7c,0xbf4a3e2f,0xbf7ebf13,0x3dfbbf51,0xbf7fbecf,0xbd97bf6a,0x3f27beb8,0x3f423f6f,
0x3efcbf09,0x3f5f3f58,0x3e893f7a,0xbf77be60,0xbef13f22,0xbf62bf46,0x3ef1bf22,0x3f623f46,0xbe95bf7f,0x3f753dc9,0x3e953f7f,0xbf75bdc9,
0x3f623f46,0xbef13f22,0xbf62bf46,0x3ef1bf22,0xbf75bdc9,0xbe95bf7f,0x3f753dc9,0x3e953f7f,0x3f1dbf13,0x3f4a3f51,0xbf7ebe2f,0xbdfbbf7c,
0xbd973f6f,0xbf7fbeb8,0x3f42becf,0x3f273f6a,0xbefcbf7a,0x3f5fbe60,0xbe893f58,0xbf77bf09,0x3f653f31,0xbee63f39,0xbea1bf80,0x3f73bcc9,
0xbf3e3f04,0xbf2cbf5c,0x3f2c3f5c,0xbf3e3f04,0x3edbbf4e,0x3f673f18,0xbf67bf18,0x3edbbf4e,0xbd493f78,0xbf80be79,0x3f803e79,0xbd493f78,
0xbeacbf7d,0x3f71be16,0xbf713e16,0xbeacbf7d,0x3f58bee6,0x3f093f65,0x3e60bf73,0x3f7a3ea1,0xbf393f1d,0xbf31bf4a,0xbcc93f7e,0xbf80bdfb,
0x3f13bf42,0x3f513f27,0xbe2fbf7f,0x3f7cbd97,0xbecf3f5f,0xbf6abefc,0x3eb83f77,0xbf6f3e89,0xbf6d3ec4,0xbec4bf6d,0xbf6d3ec4,0xbec4bf6d,
0x3f6dbec4,0x3ec43f6d,0x3f6dbec4,0x3ec43f6d,0xbf6d3ec4,0xbec4bf6d,0xbf6d3ec4,0xbec4bf6d,0x3f6dbec4,0x3ec43f6d,0x3f6dbec4,0x3ec43f6d,
0x3f7abea1,0x3e603f73,0x3f583ee6,0xbf093f65,0xbf803dfb,0xbcc9bf7e,0xbf39bf1d,0x3f31bf4a,0x3f7c3d97,0xbe2f3f7f,0x3f133f42,0xbf513f27,
0xbf6fbe89,0x3eb8bf77,0xbecfbf5f,0x3f6abefc,0xbf803e79,0xbd49bf78,0xbd49bf78,0x3f80be79,0x3f713e16,0xbeac3f7d,0xbeac3f7d,0xbf71be16,
0xbf3ebf04,0x3f2cbf5c,0x3f2cbf5c,0x3f3e3f04,0x3edb3f4e,0xbf673f18,0xbf673f18,0xbedbbf4e,0x3f7ebe2f,0xbdfb3f7c,0xbf4a3f51,0xbf1dbf13,
0xbf42becf,0x3f27bf6a,0x3f7fbeb8,0x3d973f6f,0x3e893f58,0xbf773f09,0xbf5fbe60,0x3efcbf7a,0x3ea1bf80,0x3f733cc9,0x3ee63f39,0xbf653f31,
0xbf753dc9,0x3e95bf7f,0x3f75bdc9,0xbe953f7f,0x3ef13f22,0xbf623f46,0xbef1bf22,0x3f62bf46,0x3e95bf7f,0x3f75bdc9,0xbe953f7f,0xbf753dc9,
0xbf623f46,0xbef1bf22,0x3f62bf46,0x3ef13f22,0x3f65bcc9,0xbee63f80,0xbea1bf31,0x3f73bf39,0xbdfbbf51,0x3f7ebf13,0xbf1d3f7c,0xbf4abe2f,
0xbf423f6f,0xbf27beb8,0x3f7fbecf,0xbd973f6a,0x3f77be60,0xbe893f7a,0xbefcbf09,0x3f5fbf58,0xbf4ebd49,0x3f18bf80,0xbf183f80,0xbf4ebd49,
0xbe793f71,0xbf783eac,0x3f78beac,0xbe793f71,0x3f7dbf2c,0x3e163f3e,0xbe16bf3e,0x3f7dbf2c,0xbf04bedb,0x3f5cbf67,0xbf5c3f67,0xbf04bedb,
0x3f313dfb,0xbf393f7e,0x3f80bf1d,0xbcc93f4a,0x3f13bf7f,0x3f51bd97,0xbe2fbf27,0x3f7cbf42,0xbf6a3e89,0x3ecfbf77,0xbf6f3f5f,0xbeb8befc,
0xbe603f65,0xbf7a3ee6,0x3f093ea1,0xbf583f73,0xbf0ebe48,0x3f55bf7b,0xbf0ebe48,0x3f55bf7b,0xbf553f7b,0xbf0ebe48,0xbf553f7b,0xbf0ebe48,
0x3f0e3e48,0xbf553f7b,0x3f0e3e48,0xbf553f7b,0x3f55bf7b,0x3f0e3e48,0x3f55bf7b,0x3f0e3e48,0x3ecf3e89,0xbf6a3f77,0xbeb83f5f,0xbf6f3efc,
0x3f7abf65,0x3e603ee6,0x3f58bea1,0xbf093f73,0xbcc9bf1d,0x3f80bf4a,0x3f31bf7e,0x3f39bdfb,0xbf7c3f27,0x3e2fbf42,0xbf13bd97,0x3f51bf7f,
0xbe79beac,0x3f78bf71,0x3f78bf71,0x3e793eac,0xbf7d3f3e,0x3e16bf2c,0x3e16bf2c,0x3f7dbf3e,0xbf043f67,0xbf5c3edb,0xbf5c3edb,0x3f04bf67,
0x3f18bd49,0xbf4e3f80,0xbf4e3f80,0xbf183d49,0x3d973ecf,0xbf7f3f6a,0xbf423eb8,0x3f27bf6f,0x3f5fbf09,0xbefc3f58,0xbf773f7a,0xbe89be60,
0x3f65bf80,0x3ee63cc9,0xbea13f39,0xbf733f31,0x3dfbbf13,0x3f7ebf51,0x3f1dbe2f,0xbf4a3f7c,0x3dc9bef1,0x3f7fbf62,0xbdc93ef1,0xbf7f3f62,
0xbf223e95,0x3f46bf75,0x3f22be95,0xbf463f75,0xbf7f3f62,0x3dc9bef1,0x3f7fbf62,0xbdc93ef1,0xbf463f75,0xbf223e95,0x3f46bf75,0x3f22be95,
0xbe893f09,0xbf773f58,0x3f5fbf7a,0x3efcbe60,0x3ea1bcc9,0xbf733f80,0x3ee6bf31,0x3f65bf39,0x3f4abf13,0xbf1d3f51,0xbdfbbe2f,0x3f7ebf7c,
0x3f7fbf6f,0xbd973eb8,0xbf273ecf,0x3f42bf6a,0x3edbbf18,0x3f67bf4e,0xbf673f4e,0x3edbbf18,0x3d49be79,0x3f80bf78,0xbf803f78,0x3d49be79,
0xbeac3e16,0x3f71bf7d,0xbf713f7d,0xbeac3e16,0xbf2c3f04,0x3f3ebf5c,0xbf3e3f5c,0xbf2c3f04,0xbf133f27,0xbf513f42,0x3e2fbd97,0xbf7c3f7f,
0xbecf3efc,0xbf6a3f5f,0x3eb8be89,0xbf6f3f77,0xbe603ea1,0xbf7a3f73,0x3f09bee6,0xbf583f65,0xbcc93dfb,0xbf803f7e,0x3f31bf1d,0xbf393f4a,
0x3f803f80,0xbf353f35,0x3f803f80,0xbf353f35,0x3f803f80,0xbf353f35,0x3f803f80,0xbf353f35,0x3f803f80,0xbf353f35,0x3f803f80,0xbf353f35,
0x3f803f80,0xbf353f35,0x3f803f80,0xbf353f35,0x3e2f3d97,0x3f7c3f7f,0x3f513f42,0x3f133f27,0x3eb83e89,0x3f6f3f77,0x3f6a3f5f,0x3ecf3efc,
0x3f093ee6,0x3f583f65,0x3f7a3f73,0x3e603ea1,0x3f313f1d,0x3f393f4a,0x3f803f7e,0x3cc93dfb,0xbf71bf7d,0x3eac3e16,0x3eac3e16,0x3f713f7d,
0xbf3ebf5c,0x3f2c3f04,0x3f2c3f04,0x3f3e3f5c,0xbedbbf18,0x3f673f4e,0x3f673f4e,0x3edb3f18,0xbd49be79,0x3f803f78,0x3f803f78,0x3d493e79,
0xbefcbe60,0xbf5fbf7a,0xbe89bf09,0x3f773f58,0xbf65bf39,0xbee6bf31,0x3ea13cc9,0x3f733f80,0xbf7ebf7c,0x3dfbbe2f,0x3f4a3f13,0x3f1d3f51,
0xbf42bf6a,0x3f273ecf,0x3f7f3f6f,0x3d973eb8,0x3f463f75,0xbf22be95,0xbf46bf75,0x3f223e95,0x3dc93ef1,0xbf7fbf62,0xbdc9bef1,0x3f7f3f62,
0xbf22be95,0xbf46bf75,0x3f223e95,0x3f463f75,0xbf7fbf62,0xbdc9bef1,0x3f7f3f62,0x3dc93ef1,0x3f423eb8,0x3f273f6f,0xbf7fbf6a,0x3d97becf,
0x3f773f7a,0xbe893e60,0xbefcbf58,0x3f5f3f09,0x3ea13f39,0xbf73bf31,0x3ee6bcc9,0x3f653f80,0xbf1dbe2f,0xbf4abf7c,0x3f7e3f51,0x3dfb3f13,
0xbf04bf67,0x3f5c3edb,0xbf5cbedb,0xbf04bf67,0x3f183d49,0x3f4e3f80,0xbf4ebf80,0x3f183d49,0x3f783f71,0xbe793eac,0x3e79beac,0x3f783f71,
0x3e163f2c,0xbf7dbf3e,0x3f7d3f3e,0x3e163f2c,0xbf6fbefc,0xbeb8bf5f,0xbecf3e89,0xbf6abf77,0xbf09bf73,0x3f583ea1,0xbf7abf65,0x3e60bee6,
0x3f393dfb,0x3f313f7e,0x3cc9bf1d,0x3f803f4a,0x3f513f7f,0xbf133d97,0x3f7c3f27,0x3e2f3f42,0x3e483f55,0xbf7bbf0e,0x3e483f55,0xbf7bbf0e,
0xbf7bbf0e,0xbe48bf55,0xbf7bbf0e,0xbe48bf55,0xbe48bf55,0x3f7b3f0e,0xbe48bf55,0x3f7b3f0e,0x3f7b3f0e,0x3e483f55,0x3f7b3f0e,0x3e483f55,
0x3f803f1d,0x3cc93f4a,0x3f393f7e,0xbf313dfb,0xbe2f3f27,0xbf7cbf42,0xbf51bd97,0xbf13bf7f,0xbf6fbf5f,0x3eb8befc,0xbecfbf77,0x3f6a3e89,
0x3f09bea1,0x3f583f73,0x3f7a3ee6,0x3e603f65,0x3e16bf3e,0x3f7d3f2c,0x3f7d3f2c,0xbe163f3e,0x3f5c3f67,0xbf043edb,0xbf043edb,0xbf5cbf67,
0xbf4e3d49,0xbf18bf80,0xbf18bf80,0x3f4ebd49,0xbe79bf71,0x3f783eac,0x3f783eac,0x3e793f71,0xbf73bf39,0x3ea1bf31,0x3f653cc9,0x3ee63f80,
0x3f4abe2f,0x3f1d3f7c,0xbdfb3f51,0xbf7ebf13,0x3d973f6a,0xbf7fbecf,0xbf42bf6f,0x3f27beb8,0xbf5fbf58,0x3efcbf09,0x3f773e60,0x3e893f7a,
0xbef13f22,0xbf62bf46,0x3ef1bf22,0x3f623f46,0xbe95bf7f,0x3f753dc9,0x3e953f7f,0xbf75bdc9,0x3f623f46,0xbef13f22,0xbf62bf46,0x3ef1bf22,
0xbf75bdc9,0xbe95bf7f,0x3f753dc9,0x3e953f7f,0x3f4a3f51,0xbf1d3f13,0xbdfbbf7c,0x3f7e3e2f,0xbf7fbeb8,0x3d97bf6f,0x3f273f6a,0xbf423ecf,
0x3f5fbe60,0x3efc3f7a,0xbf77bf09,0x3e89bf58,0xbee63f39,0xbf65bf31,0x3f73bcc9,0x3ea13f80,0x3f3ebf04,0x3f2c3f5c,0xbf2cbf5c,0x3f3ebf04,
0xbedb3f4e,0xbf67bf18,0x3f673f18,0xbedb3f4e,0x3d49bf78,0x3f803e79,0xbf80be79,0x3d49bf78,0x3eac3f7d,0xbf713e16,0x3f71be16,0x3eac3f7d,
0xbf09bf65,0x3f58bee6,0xbf7abea1,0x3e60bf73,0x3f313f4a,0xbf393f1d,0x3f803dfb,0xbcc93f7e,0xbf51bf27,0x3f13bf42,0xbf7c3d97,0xbe2fbf7f,
0x3f6a3efc,0xbecf3f5f,0x3f6fbe89,0x3eb83f77,0xbf6d3ec4,0xbec4bf6d,0xbf6d3ec4,0xbec4bf6d,0x3f6dbec4,0x3ec43f6d,0x3f6dbec4,0x3ec43f6d,
0xbf6d3ec4,0xbec4bf6d,0xbf6d3ec4,0xbec4bf6d,0x3f6dbec4,0x3ec43f6d,0x3f6dbec4,0x3ec43f6d,0x3e603f73,0xbf7a3ea1,0xbf093f65,0xbf58bee6,
0xbcc9bf7e,0x3f80bdfb,0x3f31bf4a,0x3f393f1d,0xbe2f3f7f,0xbf7cbd97,0xbf513f27,0xbf13bf42,0x3eb8bf77,0x3f6f3e89,0x3f6abefc,0x3ecf3f5f,
0x3f80be79,0x3d493f78,0x3d493f78,0xbf803e79,0xbf71be16,0x3eacbf7d,0x3eacbf7d,0x3f713e16,0x3f3e3f04,0xbf2c3f5c,0xbf2c3f5c,0xbf3ebf04,
0xbedbbf4e,0x3f67bf18,0x3f67bf18,0x3edb3f4e,0x3dfbbf7c,0x3f7ebe2f,0x3f1d3f13,0xbf4a3f51,0xbf273f6a,0xbf42becf,0xbd97bf6f,0x3f7fbeb8,
0x3f77bf09,0x3e893f58,0xbefc3f7a,0xbf5fbe60,0xbf73bcc9,0x3ea1bf80,0x3f65bf31,0x3ee63f39,0xbf753dc9,0x3e95bf7f,0x3f75bdc9,0xbe953f7f,
0x3ef13f22,0xbf623f46,0xbef1bf22,0x3f62bf46,0x3e95bf7f,0x3f75bdc9,0xbe953f7f,0xbf753dc9,0xbf623f46,0xbef1bf22,0x3f62bf46,0x3ef13f22,
0xbee63f80,0xbf653cc9,0x3f73bf39,0x3ea13f31,0x3f7ebf13,0x3dfb3f51,0xbf4abe2f,0x3f1dbf7c,0xbf27beb8,0x3f42bf6f,0xbd973f6a,0xbf7f3ecf,
0xbe893f7a,0xbf773e60,0x3f5fbf58,0x3efc3f09,0x3f4e3d49,0xbf183f80,0x3f18bf80,0x3f4e3d49,0x3e79bf71,0x3f78beac,0xbf783eac,0x3e79bf71,
0xbf7d3f2c,0xbe16bf3e,0x3e163f3e,0xbf7d3f2c,0x3f043edb,0xbf5c3f67,0x3f5cbf67,0x3f043edb,0x3f39bf7e,0x3f313dfb,0x3cc9bf4a,0x3f80bf1d,
0xbf513d97,0x3f13bf7f,0xbf7c3f42,0xbe2fbf27,0xbecf3f77,0xbf6a3e89,0x3eb83efc,0xbf6f3f5f,0x3f7abee6,0xbe603f65,0x3f58bf73,0x3f093ea1,
0xbf0ebe48,0x3f55bf7b,0xbf0ebe48,0x3f55bf7b,0xbf553f7b,0xbf0ebe48,0xbf553f7b,0xbf0ebe48,0x3f0e3e48,0xbf553f7b,0x3f0e3e48,0xbf553f7b,
0x3f55bf7b,0x3f0e3e48,0x3f55bf7b,0x3f0e3e48,0xbf6a3f77,0xbecfbe89,0xbf6f3efc,0x3eb8bf5f,0x3e603ee6,0xbf7a3f65,0xbf093f73,0xbf583ea1,
0x3f80bf4a,0x3cc93f1d,0x3f39bdfb,0xbf313f7e,0x3e2fbf42,0x3f7cbf27,0x3f51bf7f,0x3f133d97,0x3e793eac,0xbf783f71,0xbf783f71,0xbe79beac,
0x3f7dbf3e,0xbe163f2c,0xbe163f2c,0xbf7d3f3e,0x3f04bf67,0x3f5cbedb,0x3f5cbedb,0xbf043f67,0xbf183d49,0x3f4ebf80,0x3f4ebf80,0x3f18bd49,
0x3f7fbf6a,0x3d973ecf,0xbf273f6f,0xbf423eb8,0x3efcbf58,0x3f5fbf09,0x3e893e60,0xbf773f7a,0xbee6bcc9,0x3f65bf80,0x3f73bf31,0xbea13f39,
0xbf7e3f51,0x3dfbbf13,0x3f4abf7c,0x3f1dbe2f,0x3dc9bef1,0x3f7fbf62,0xbdc93ef1,0xbf7f3f62,0xbf223e95,0x3f46bf75,0x3f22be95,0xbf463f75,
0xbf7f3f62,0x3dc9bef1,0x3f7fbf62,0xbdc93ef1,0xbf463f75,0xbf223e95,0x3f46bf75,0x3f22be95,0xbf773f58,0x3e89bf09,0x3efcbe60,0xbf5f3f7a,
0xbf733f80,0xbea13cc9,0x3f65bf39,0xbee63f31,0xbf1d3f51,0xbf4a3f13,0x3f7ebf7c,0x3dfb3e2f,0xbd973eb8,0xbf7f3f6f,0x3f42bf6a,0x3f27becf,
0xbedb3f18,0xbf673f4e,0x3f67bf4e,0xbedb3f18,0xbd493e79,0xbf803f78,0x3f80bf78,0xbd493e79,0x3eacbe16,0xbf713f7d,0x3f71bf7d,0x3eacbe16,
0x3f2cbf04,0xbf3e3f5c,0x3f3ebf5c,0x3f2cbf04,0x3f51bf42,0xbf133f27,0x3f7cbf7f,0x3e2fbd97,0x3f6abf5f,0xbecf3efc,0x3f6fbf77,0x3eb8be89,
0x3f7abf73,0xbe603ea1,0x3f58bf65,0x3f09bee6,0x3f80bf7e,0xbcc93dfb,0x3f39bf4a,0x3f31bf1d,0x3f803f80,0x3f803f80,0x3f803f80,0x3f803f80,
0x0,0x0,0x0,0x0,0x3f803f80,0x3f803f80,0x3f803f80,0x3f803f80,0x0,0x0,0x0,0x0,
0x3f803f80,0x3f803f80,0x3f803f80,0x3f803f80,0x0,0x0,0x0,0x0,0x3f803f80,0x3f803f80,0x3f803f80,0x3f803f80,
0x0,0x0,0x0,0x0,0x3e480000,0x3f0e3ec4,0x3f553f35,0x3f7b3f6d,0x3f7b3f80,0x3f553f6d,0x3f0e3f35,0x3e483ec4,
0x3f7b3f80,0x3f553f6d,0x3f0e3f35,0x3e483ec4,0xbe480000,0xbf0ebec4,0xbf55bf35,0xbf7bbf6d,0xbe480000,0xbf0ebec4,0xbf55bf35,0xbf7bbf6d,
0xbf7bbf80,0xbf55bf6d,0xbf0ebf35,0xbe48bec4,0xbf7bbf80,0xbf55bf6d,0xbf0ebf35,0xbe48bec4,0x3e480000,0x3f0e3ec4,0x3f553f35,0x3f7b3f6d,
0xbf6dbf80,0xbec4bf35,0x3ec40000,0x3f6d3f35,0xbec40000,0xbf6dbf35,0xbf6dbf80,0xbec4bf35,0x3f6d3f80,0x3ec43f35,0xbec40000,0xbf6dbf35,
0x3ec40000,0x3f6d3f35,0x3f6d3f80,0x3ec43f35,0xbf6dbf80,0xbec4bf35,0x3ec40000,0x3f6d3f35,0xbec40000,0xbf6dbf35,0xbf6dbf80,0xbec4bf35,
0x3f6d3f80,0x3ec43f35,0xbec40000,0xbf6dbf35,0x3ec40000,0x3f6d3f35,0x3f6d3f80,0x3ec43f35,0xbf55bf80,0x3e48bec4,0x3f7b3f35,0x3f0e3f6d,
0x3f0e0000,0x3f7b3f6d,0x3e483f35,0xbf55bec4,0x3f0e0000,0x3f7b3f6d,0x3e483f35,0xbf55bec4,0x3f553f80,0xbe483ec4,0xbf7bbf35,0xbf0ebf6d,
0x3f553f80,0xbe483ec4,0xbf7bbf35,0xbf0ebf6d,0xbf0e0000,0xbf7bbf6d,0xbe48bf35,0x3f553ec4,0xbf0e0000,0xbf7bbf6d,0xbe48bf35,0x3f553ec4,
0xbf55bf80,0x3e48bec4,0x3f7b3f35,0x3f0e3f6d,0x3f353f80,0xbf350000,0xbf35bf80,0x3f350000,0x3f350000,0x3f353f80,0xbf350000,0xbf35bf80,
0x3f353f80,0xbf350000,0xbf35bf80,0x3f350000,0x3f350000,0x3f353f80,0xbf350000,0xbf35bf80,0x3f353f80,0xbf350000,0xbf35bf80,0x3f350000,
0x3f350000,0x3f353f80,0xbf350000,0xbf35bf80,0x3f353f80,0xbf350000,0xbf35bf80,0x3f350000,0x3f350000,0x3f353f80,0xbf350000,0xbf35bf80,
0xbf550000,0xbe48bf6d,0x3f7b3f35,0xbf0e3ec4,0xbf0ebf80,0x3f7b3ec4,0xbe483f35,0xbf55bf6d,0xbf0ebf80,0x3f7b3ec4,0xbe483f35,0xbf55bf6d,
0x3f550000,0x3e483f6d,0xbf7bbf35,0x3f0ebec4,0x3f550000,0x3e483f6d,0xbf7bbf35,0x3f0ebec4,0x3f0e3f80,0xbf7bbec4,0x3e48bf35,0x3f553f6d,
0x3f0e3f80,0xbf7bbec4,0x3e48bf35,0x3f553f6d,0xbf550000,0xbe48bf6d,0x3f7b3f35,0xbf0e3ec4,0xbec4bf80,0x3f6d3f35,0xbf6d0000,0x3ec4bf35,
0xbf6d0000,0x3ec4bf35,0x3ec43f80,0xbf6dbf35,0x3ec43f80,0xbf6dbf35,0x3f6d0000,0xbec43f35,0x3f6d0000,0xbec43f35,0xbec4bf80,0x3f6d3f35,
0xbec4bf80,0x3f6d3f35,0xbf6d0000,0x3ec4bf35,0xbf6d0000,0x3ec4bf35,0x3ec43f80,0xbf6dbf35,0x3ec43f80,0xbf6dbf35,0x3f6d0000,0xbec43f35,
0x3f6d0000,0xbec43f35,0xbec4bf80,0x3f6d3f35,0x3e483f80,0xbf0ebf6d,0x3f553f35,0xbf7bbec4,0xbf7b0000,0x3f55bec4,0xbf0e3f35,0x3e48bf6d,
0xbf7b0000,0x3f55bec4,0xbf0e3f35,0x3e48bf6d,0xbe48bf80,0x3f0e3f6d,0xbf55bf35,0x3f7b3ec4,0xbe48bf80,0x3f0e3f6d,0xbf55bf35,0x3f7b3ec4,
0x3f7b0000,0xbf553ec4,0x3f0ebf35,0xbe483f6d,0x3f7b0000,0xbf553ec4,0x3f0ebf35,0xbe483f6d,0x3e483f80,0xbf0ebf6d,0x3f553f35,0xbf7bbec4,
0x80008000,0x80008000,0x80008000,0x80008000,0x3f803f80,0x3f803f80,0x3f803f80,0x3f803f80,0x80008000,0x80008000,0x80008000,0x80008000,
0x3f803f80,0x3f803f80,0x3f803f80,0x3f803f80,0x80008000,0x80008000,0x80008000,0x80008000,0x3f803f80,0x3f803f80,0x3f803f80,0x3f803f80,
0x80008000,0x80008000,0x80008000,0x80008000,0x3f803f80,0x3f803f80,0x3f803f80,0x3f803f80,0x3f7b3f80,0x3f553f6d,0x3f0e3f35,0x3e483ec4,
0xbe488000,0xbf0ebec4,0xbf55bf35,0xbf7bbf6d,0xbe480000,0xbf0ebec4,0xbf55bf35,0xbf7bbf6d,0xbf7bbf80,0xbf55bf6d,0xbf0ebf35,0xbe48bec4,
0xbf7bbf80,0xbf55bf6d,0xbf0ebf35,0xbe48bec4,0x3e488000,0x3f0e3ec4,0x3f553f35,0x3f7b3f6d,0x3e480000,0x3f0e3ec4,0x3f553f35,0x3f7b3f6d,
0x3f7b3f80,0x3f553f6d,0x3f0e3f35,0x3e483ec4,0x3ec48000,0x3f6d3f35,0x3f6d3f80,0x3ec43f35,0xbf6dbf80,0xbec4bf35,0x3ec40000,0x3f6d3f35,
0xbec48000,0xbf6dbf35,0xbf6dbf80,0xbec4bf35,0x3f6d3f80,0x3ec43f35,0xbec40000,0xbf6dbf35,0x3ec48000,0x3f6d3f35,0x3f6d3f80,0x3ec43f35,
0xbf6dbf80,0xbec4bf35,0x3ec40000,0x3f6d3f35,0xbec48000,0xbf6dbf35,0xbf6dbf80,0xbec4bf35,0x3f6d3f80,0x3ec43f35,0xbec40000,0xbf6dbf35,
0x3f0e0000,0x3f7b3f6d,0x3e483f35,0xbf55bec4,0x3f553f80,0xbe483ec4,0xbf7bbf35,0xbf0ebf6d,0x3f553f80,0xbe483ec4,0xbf7bbf35,0xbf0ebf6d,
0xbf0e8000,0xbf7bbf6d,0xbe48bf35,0x3f553ec4,0xbf0e0000,0xbf7bbf6d,0xbe48bf35,0x3f553ec4,0xbf55bf80,0x3e48bec4,0x3f7b3f35,0x3f0e3f6d,
0xbf55bf80,0x3e48bec4,0x3f7b3f35,0x3f0e3f6d,0x3f0e8000,0x3f7b3f6d,0x3e483f35,0xbf55bec4,0xbf358000,0xbf35bf80,0x3f358000,0x3f353f80,
0x3f353f80,0xbf350000,0xbf35bf80,0x3f350000,0xbf358000,0xbf35bf80,0x3f358000,0x3f353f80,0x3f353f80,0xbf350000,0xbf35bf80,0x3f350000,
0xbf358000,0xbf35bf80,0x3f358000,0x3f353f80,0x3f353f80,0xbf350000,0xbf35bf80,0x3f350000,0xbf358000,0xbf35bf80,0x3f358000,0x3f353f80,
0x3f353f80,0xbf350000,0xbf35bf80,0x3f350000,0xbf0ebf80,0x3f7b3ec4,0xbe483f35,0xbf55bf6d,0x3f558000,0x3e483f6d,0xbf7bbf35,0x3f0ebec4,
0x3f550000,0x3e483f6d,0xbf7bbf35,0x3f0ebec4,0x3f0e3f80,0xbf7bbec4,0x3e48bf35,0x3f553f6d,0x3f0e3f80,0xbf7bbec4,0x3e48bf35,0x3f553f6d,
0xbf558000,0xbe48bf6d,0x3f7b3f35,0xbf0e3ec4,0xbf550000,0xbe48bf6d,0x3f7b3f35,0xbf0e3ec4,0xbf0ebf80,0x3f7b3ec4,0xbe483f35,0xbf55bf6d,
0x3f6d8000,0xbec43f35,0xbec4bf80,0x3f6d3f35,0xbec4bf80,0x3f6d3f35,0xbf6d0000,0x3ec4bf35,0xbf6d8000,0x3ec4bf35,0x3ec43f80,0xbf6dbf35,
0x3ec43f80,0xbf6dbf35,0x3f6d0000,0xbec43f35,0x3f6d8000,0xbec43f35,0xbec4bf80,0x3f6d3f35,0xbec4bf80,0x3f6d3f35,0xbf6d0000,0x3ec4bf35,
0xbf6d8000,0x3ec4bf35,0x3ec43f80,0xbf6dbf35,0x3ec43f80,0xbf6dbf35,0x3f6d0000,0xbec43f35,0xbf7b0000,0x3f55bec4,0xbf0e3f35,0x3e48bf6d,
0xbe48bf80,0x3f0e3f6d,0xbf55bf35,0x3f7b3ec4,0xbe48bf80,0x3f0e3f6d,0xbf55bf35,0x3f7b3ec4,0x3f7b8000,0xbf553ec4,0x3f0ebf35,0xbe483f6d,
0x3f7b0000,0xbf553ec4,0x3f0ebf35,0xbe483f6d,0x3e483f80,0xbf0ebf6d,0x3f553f35,0xbf7bbec4,0x3e483f80,0xbf0ebf6d,0x3f553f35,0xbf7bbec4,
0xbf7b8000,0x3f55bec4,0xbf0e3f35,0x3e48bf6d,0x3f80,0xbf80,0x3f80,0xbf80,0x3f800000,0xbf800000,0x3f800000,0xbf800000,
0x3f80,0xbf80,0x3f80,0xbf80,0x3f800000,0xbf800000,0x3f800000,0xbf800000,0x3f80,0xbf80,0x3f80,0xbf80,
0x3f800000,0xbf800000,0x3f800000,0xbf800000,0x3f80,0xbf80,0x3f80,0xbf80,0x3f800000,0xbf800000,0x3f800000,0xbf800000,
0x3f7b0000,0xbf55bec4,0x3f0e3f35,0xbe48bf6d,0xbe483f80,0x3f0ebf6d,0xbf553f35,0x3f7bbec4,0xbe483f80,0x3f0ebf6d,0xbf553f35,0x3f7bbec4,
0xbf7b0000,0x3f553ec4,0xbf0ebf35,0x3e483f6d,0xbf7b0000,0x3f553ec4,0xbf0ebf35,0x3e483f6d,0x3e48bf80,0xbf0e3f6d,0x3f55bf35,0xbf7b3ec4,
0x3e48bf80,0xbf0e3f6d,0x3f55bf35,0xbf7b3ec4,0x3f7b0000,0xbf55bec4,0x3f0e3f35,0xbe48bf6d,0x3ec4bf80,0xbf6d3f35,0x3f6d0000,0xbec4bf35,
0xbf6d0000,0x3ec43f35,0x3ec4bf80,0xbf6d3f35,0xbec43f80,0x3f6dbf35,0xbf6d0000,0x3ec43f35,0x3f6d0000,0xbec4bf35,0xbec43f80,0x3f6dbf35,
0x3ec4bf80,0xbf6d3f35,0x3f6d0000,0xbec4bf35,0xbf6d0000,0x3ec43f35,0x3ec4bf80,0xbf6d3f35,0xbec43f80,0x3f6dbf35,0xbf6d0000,0x3ec43f35,
0x3f6d0000,0xbec4bf35,0xbec43f80,0x3f6dbf35,0x3f0ebf80,0xbf7b3ec4,0x3e483f35,0x3f55bf6d,0x3f550000,0x3e48bf6d,0xbf7b3f35,0x3f0e3ec4,
0x3f550000,0x3e48bf6d,0xbf7b3f35,0x3f0e3ec4,0xbf0e3f80,0x3f7bbec4,0xbe48bf35,0xbf553f6d,0xbf0e3f80,0x3f7bbec4,0xbe48bf35,0xbf553f6d,
0xbf550000,0xbe483f6d,0x3f7bbf35,0xbf0ebec4,0xbf550000,0xbe483f6d,0x3f7bbf35,0xbf0ebec4,0x3f0ebf80,0xbf7b3ec4,0x3e483f35,0x3f55bf6d,
0xbf353f80,0x3f350000,0x3f35bf80,0xbf350000,0x3f350000,0x3f35bf80,0xbf350000,0xbf353f80,0xbf353f80,0x3f350000,0x3f35bf80,0xbf350000,
0x3f350000,0x3f35bf80,0xbf350000,0xbf353f80,0xbf353f80,0x3f350000,0x3f35bf80,0xbf350000,0x3f350000,0x3f35bf80,0xbf350000,0xbf353f80,
0xbf353f80,0x3f350000,0x3f35bf80,0xbf350000,0x3f350000,0x3f35bf80,0xbf350000,0xbf353f80,0xbf0e0000,0xbf7b3f6d,0xbe483f35,0x3f55bec4,
0x3f55bf80,0xbe48bec4,0xbf7b3f35,0xbf0e3f6d,0x3f55bf80,0xbe48bec4,0xbf7b3f35,0xbf0e3f6d,0x3f0e0000,0x3f7bbf6d,0x3e48bf35,0xbf553ec4,
0x3f0e0000,0x3f7bbf6d,0x3e48bf35,0xbf553ec4,0xbf553f80,0x3e483ec4,0x3f7bbf35,0x3f0ebf6d,0xbf553f80,0x3e483ec4,0x3f7bbf35,0x3f0ebf6d,
0xbf0e0000,0xbf7b3f6d,0xbe483f35,0x3f55bec4,0x3f6dbf80,0x3ec4bf35,0xbec40000,0xbf6d3f35,0xbec40000,0xbf6d3f35,0xbf6d3f80,0xbec43f35,
0xbf6d3f80,0xbec43f35,0x3ec40000,0x3f6dbf35,0x3ec40000,0x3f6dbf35,0x3f6dbf80,0x3ec4bf35,0x3f6dbf80,0x3ec4bf35,0xbec40000,0xbf6d3f35,
0xbec40000,0xbf6d3f35,0xbf6d3f80,0xbec43f35,0xbf6d3f80,0xbec43f35,0x3ec40000,0x3f6dbf35,0x3ec40000,0x3f6dbf35,0x3f6dbf80,0x3ec4bf35,
0xbf7b3f80,0xbf553f6d,0xbf0e3f35,0xbe483ec4,0xbe480000,0xbf0e3ec4,0xbf553f35,0xbf7b3f6d,0xbe480000,0xbf0e3ec4,0xbf553f35,0xbf7b3f6d,
0x3f7bbf80,0x3f55bf6d,0x3f0ebf35,0x3e48bec4,0x3f7bbf80,0x3f55bf6d,0x3f0ebf35,0x3e48bec4,0x3e480000,0x3f0ebec4,0x3f55bf35,0x3f7bbf6d,
0x3e480000,0x3f0ebec4,0x3f55bf35,0x3f7bbf6d,0xbf7b3f80,0xbf553f6d,0xbf0e3f35,0xbe483ec4,0xbf808000,0x3f808000,0xbf808000,0x3f808000,
0x3f80,0xbf80,0x3f80,0xbf80,0xbf808000,0x3f808000,0xbf808000,0x3f808000,0x3f80,0xbf80,0x3f80,0xbf80,
0xbf808000,0x3f808000,0xbf808000,0x3f808000,0x3f80,0xbf80,0x3f80,0xbf80,0xbf808000,0x3f808000,0xbf808000,0x3f808000,
0x3f80,0xbf80,0x3f80,0xbf80,0xbe483f80,0x3f0ebf6d,0xbf553f35,0x3f7bbec4,0xbf7b8000,0x3f553ec4,0xbf0ebf35,0x3e483f6d,
0xbf7b0000,0x3f553ec4,0xbf0ebf35,0x3e483f6d,0x3e48bf80,0xbf0e3f6d,0x3f55bf35,0xbf7b3ec4,0x3e48bf80,0xbf0e3f6d,0x3f55bf35,0xbf7b3ec4,
0x3f7b8000,0xbf55bec4,0x3f0e3f35,0xbe48bf6d,0x3f7b0000,0xbf55bec4,0x3f0e3f35,0xbe48bf6d,0xbe483f80,0x3f0ebf6d,0xbf553f35,0x3f7bbec4,
0x3f6d8000,0xbec4bf35,0xbec43f80,0x3f6dbf35,0x3ec4bf80,0xbf6d3f35,0x3f6d0000,0xbec4bf35,0xbf6d8000,0x3ec43f35,0x3ec4bf80,0xbf6d3f35,
0xbec43f80,0x3f6dbf35,0xbf6d0000,0x3ec43f35,0x3f6d8000,0xbec4bf35,0xbec43f80,0x3f6dbf35,0x3ec4bf80,0xbf6d3f35,0x3f6d0000,0xbec4bf35,
0xbf6d8000,0x3ec43f35,0x3ec4bf80,0xbf6d3f35,0xbec43f80,0x3f6dbf35,0xbf6d0000,0x3ec43f35,0x3f550000,0x3e48bf6d,0xbf7b3f35,0x3f0e3ec4,
0xbf0e3f80,0x3f7bbec4,0xbe48bf35,0xbf553f6d,0xbf0e3f80,0x3f7bbec4,0xbe48bf35,0xbf553f6d,0xbf558000,0xbe483f6d,0x3f7bbf35,0xbf0ebec4,
0xbf550000,0xbe483f6d,0x3f7bbf35,0xbf0ebec4,0x3f0ebf80,0xbf7b3ec4,0x3e483f35,0x3f55bf6d,0x3f0ebf80,0xbf7b3ec4,0x3e483f35,0x3f55bf6d,
0x3f558000,0x3e48bf6d,0xbf7b3f35,0x3f0e3ec4,0xbf358000,0xbf353f80,0x3f358000,0x3f35bf80,0xbf353f80,0x3f350000,0x3f35bf80,0xbf350000,
0xbf358000,0xbf353f80,0x3f358000,0x3f35bf80,0xbf353f80,0x3f350000,0x3f35bf80,0xbf350000,0xbf358000,0xbf353f80,0x3f358000,0x3f35bf80,
0xbf353f80,0x3f350000,0x3f35bf80,0xbf350000,0xbf358000,0xbf353f80,0x3f358000,0x3f35bf80,0xbf353f80,0x3f350000,0x3f35bf80,0xbf350000,
0x3f55bf80,0xbe48bec4,0xbf7b3f35,0xbf0e3f6d,0x3f0e8000,0x3f7bbf6d,0x3e48bf35,0xbf553ec4,0x3f0e0000,0x3f7bbf6d,0x3e48bf35,0xbf553ec4,
0xbf553f80,0x3e483ec4,0x3f7bbf35,0x3f0ebf6d,0xbf553f80,0x3e483ec4,0x3f7bbf35,0x3f0ebf6d,0xbf0e8000,0xbf7b3f6d,0xbe483f35,0x3f55bec4,
0xbf0e0000,0xbf7b3f6d,0xbe483f35,0x3f55bec4,0x3f55bf80,0xbe48bec4,0xbf7b3f35,0xbf0e3f6d,0x3ec48000,0x3f6dbf35,0x3f6dbf80,0x3ec4bf35,
0x3f6dbf80,0x3ec4bf35,0xbec40000,0xbf6d3f35,0xbec48000,0xbf6d3f35,0xbf6d3f80,0xbec43f35,0xbf6d3f80,0xbec43f35,0x3ec40000,0x3f6dbf35,
0x3ec48000,0x3f6dbf35,0x3f6dbf80,0x3ec4bf35,0x3f6dbf80,0x3ec4bf35,0xbec40000,0xbf6d3f35,0xbec48000,0xbf6d3f35,0xbf6d3f80,0xbec43f35,
0xbf6d3f80,0xbec43f35,0x3ec40000,0x3f6dbf35,0xbe480000,0xbf0e3ec4,0xbf553f35,0xbf7b3f6d,0x3f7bbf80,0x3f55bf6d,0x3f0ebf35,0x3e48bec4,
0x3f7bbf80,0x3f55bf6d,0x3f0ebf35,0x3e48bec4,0x3e488000,0x3f0ebec4,0x3f55bf35,0x3f7bbf6d,0x3e480000,0x3f0ebec4,0x3f55bf35,0x3f7bbf6d,
0xbf7b3f80,0xbf553f6d,0xbf0e3f35,0xbe483ec4,0xbf7b3f80,0xbf553f6d,0xbf0e3f35,0xbe483ec4,0xbe488000,0xbf0e3ec4,0xbf553f35,0xbf7b3f6d,
0xbf803f80,0xbf803f80,0xbf803f80,0xbf803f80,0x0,0x0,0x0,0x0,0xbf803f80,0xbf803f80,0xbf803f80,0xbf803f80,
0x0,0x0,0x0,0x0,0xbf803f80,0xbf803f80,0xbf803f80,0xbf803f80,0x0,0x0,0x0,0x0,
0xbf803f80,0xbf803f80,0xbf803f80,0xbf803f80,0x0,0x0,0x0,0x0,0xbe480000,0xbf0e3ec4,0xbf553f35,0xbf7b3f6d,
0xbf7b3f80,0xbf553f6d,0xbf0e3f35,0xbe483ec4,0xbf7b3f80,0xbf553f6d,0xbf0e3f35,0xbe483ec4,0x3e480000,0x3f0ebec4,0x3f55bf35,0x3f7bbf6d,
0x3e480000,0x3f0ebec4,0x3f55bf35,0x3f7bbf6d,0x3f7bbf80,0x3f55bf6d,0x3f0ebf35,0x3e48bec4,0x3f7bbf80,0x3f55bf6d,0x3f0ebf35,0x3e48bec4,
0xbe480000,0xbf0e3ec4,0xbf553f35,0xbf7b3f6d,0x3f6dbf80,0x3ec4bf35,0xbec40000,0xbf6d3f35,0x3ec40000,0x3f6dbf35,0x3f6dbf80,0x3ec4bf35,
0xbf6d3f80,0xbec43f35,0x3ec40000,0x3f6dbf35,0xbec40000,0xbf6d3f35,0xbf6d3f80,0xbec43f35,0x3f6dbf80,0x3ec4bf35,0xbec40000,0xbf6d3f35,
0x3ec40000,0x3f6dbf35,0x3f6dbf80,0x3ec4bf35,0xbf6d3f80,0xbec43f35,0x3ec40000,0x3f6dbf35,0xbec40000,0xbf6d3f35,0xbf6d3f80,0xbec43f35,
0x3f55bf80,0xbe48bec4,0xbf7b3f35,0xbf0e3f6d,0xbf0e0000,0xbf7b3f6d,0xbe483f35,0x3f55bec4,0xbf0e0000,0xbf7b3f6d,0xbe483f35,0x3f55bec4,
0xbf553f80,0x3e483ec4,0x3f7bbf35,0x3f0ebf6d,0xbf553f80,0x3e483ec4,0x3f7bbf35,0x3f0ebf6d,0x3f0e0000,0x3f7bbf6d,0x3e48bf35,0xbf553ec4,
0x3f0e0000,0x3f7bbf6d,0x3e48bf35,0xbf553ec4,0x3f55bf80,0xbe48bec4,0xbf7b3f35,0xbf0e3f6d,0xbf353f80,0x3f350000,0x3f35bf80,0xbf350000,
0xbf350000,0xbf353f80,0x3f350000,0x3f35bf80,0xbf353f80,0x3f350000,0x3f35bf80,0xbf350000,0xbf350000,0xbf353f80,0x3f350000,0x3f35bf80,
0xbf353f80,0x3f350000,0x3f35bf80,0xbf350000,0xbf350000,0xbf353f80,0x3f350000,0x3f35bf80,0xbf353f80,0x3f350000,0x3f35bf80,0xbf350000,
0xbf350000,0xbf353f80,0x3f350000,0x3f35bf80,0x3f550000,0x3e48bf6d,0xbf7b3f35,0x3f0e3ec4,0x3f0ebf80,0xbf7b3ec4,0x3e483f35,0x3f55bf6d,
0x3f0ebf80,0xbf7b3ec4,0x3e483f35,0x3f55bf6d,0xbf550000,0xbe483f6d,0x3f7bbf35,0xbf0ebec4,0xbf550000,0xbe483f6d,0x3f7bbf35,0xbf0ebec4,
0xbf0e3f80,0x3f7bbec4,0xbe48bf35,0xbf553f6d,0xbf0e3f80,0x3f7bbec4,0xbe48bf35,0xbf553f6d,0x3f550000,0x3e48bf6d,0xbf7b3f35,0x3f0e3ec4,
0x3ec4bf80,0xbf6d3f35,0x3f6d0000,0xbec4bf35,0x3f6d0000,0xbec4bf35,0xbec43f80,0x3f6dbf35,0xbec43f80,0x3f6dbf35,0xbf6d0000,0x3ec43f35,
0xbf6d0000,0x3ec43f35,0x3ec4bf80,0xbf6d3f35,0x3ec4bf80,0xbf6d3f35,0x3f6d0000,0xbec4bf35,0x3f6d0000,0xbec4bf35,0xbec43f80,0x3f6dbf35,
0xbec43f80,0x3f6dbf35,0xbf6d0000,0x3ec43f35,0xbf6d0000,0x3ec43f35,0x3ec4bf80,0xbf6d3f35,0xbe483f80,0x3f0ebf6d,0xbf553f35,0x3f7bbec4,
0x3f7b0000,0xbf55bec4,0x3f0e3f35,0xbe48bf6d,0x3f7b0000,0xbf55bec4,0x3f0e3f35,0xbe48bf6d,0x3e48bf80,0xbf0e3f6d,0x3f55bf35,0xbf7b3ec4,
0x3e48bf80,0xbf0e3f6d,0x3f55bf35,0xbf7b3ec4,0xbf7b0000,0x3f553ec4,0xbf0ebf35,0x3e483f6d,0xbf7b0000,0x3f553ec4,0xbf0ebf35,0x3e483f6d,
0xbe483f80,0x3f0ebf6d,0xbf553f35,0x3f7bbec4,0x80008000,0x80008000,0x80008000,0x80008000,0xbf803f80,0xbf803f80,0xbf803f80,0xbf803f80,
0x80008000,0x80008000,0x80008000,0x80008000,0xbf803f80,0xbf803f80,0xbf803f80,0xbf803f80,0x80008000,0x80008000,0x80008000,0x80008000,
0xbf803f80,0xbf803f80,0xbf803f80,0xbf803f80,0x80008000,0x80008000,0x80008000,0x80008000,0xbf803f80,0xbf803f80,0xbf803f80,0xbf803f80,
0xbf7b3f80,0xbf553f6d,0xbf0e3f35,0xbe483ec4,0x3e488000,0x3f0ebec4,0x3f55bf35,0x3f7bbf6d,0x3e480000,0x3f0ebec4,0x3f55bf35,0x3f7bbf6d,
0x3f7bbf80,0x3f55bf6d,0x3f0ebf35,0x3e48bec4,0x3f7bbf80,0x3f55bf6d,0x3f0ebf35,0x3e48bec4,0xbe488000,0xbf0e3ec4,0xbf553f35,0xbf7b3f6d,
0xbe480000,0xbf0e3ec4,0xbf553f35,0xbf7b3f6d,0xbf7b3f80,0xbf553f6d,0xbf0e3f35,0xbe483ec4,0xbec48000,0xbf6d3f35,0xbf6d3f80,0xbec43f35,
0x3f6dbf80,0x3ec4bf35,0xbec40000,0xbf6d3f35,0x3ec48000,0x3f6dbf35,0x3f6dbf80,0x3ec4bf35,0xbf6d3f80,0xbec43f35,0x3ec40000,0x3f6dbf35,
0xbec48000,0xbf6d3f35,0xbf6d3f80,0xbec43f35,0x3f6dbf80,0x3ec4bf35,0xbec40000,0xbf6d3f35,0x3ec48000,0x3f6dbf35,0x3f6dbf80,0x3ec4bf35,
0xbf6d3f80,0xbec43f35,0x3ec40000,0x3f6dbf35,0xbf0e0000,0xbf7b3f6d,0xbe483f35,0x3f55bec4,0xbf553f80,0x3e483ec4,0x3f7bbf35,0x3f0ebf6d,
0xbf553f80,0x3e483ec4,0x3f7bbf35,0x3f0ebf6d,0x3f0e8000,0x3f7bbf6d,0x3e48bf35,0xbf553ec4,0x3f0e0000,0x3f7bbf6d,0x3e48bf35,0xbf553ec4,
0x3f55bf80,0xbe48bec4,0xbf7b3f35,0xbf0e3f6d,0x3f55bf80,0xbe48bec4,0xbf7b3f35,0xbf0e3f6d,0xbf0e8000,0xbf7b3f6d,0xbe483f35,0x3f55bec4,
0x3f358000,0x3f35bf80,0xbf358000,0xbf353f80,0xbf353f80,0x3f350000,0x3f35bf80,0xbf350000,0x3f358000,0x3f35bf80,0xbf358000,0xbf353f80,
0xbf353f80,0x3f350000,0x3f35bf80,0xbf350000,0x3f358000,0x3f35bf80,0xbf358000,0xbf353f80,0xbf353f80,0x3f350000,0x3f35bf80,0xbf350000,
0x3f358000,0x3f35bf80,0xbf358000,0xbf353f80,0xbf353f80,0x3f350000,0x3f35bf80,0xbf350000,0x3f0ebf80,0xbf7b3ec4,0x3e483f35,0x3f55bf6d,
0xbf558000,0xbe483f6d,0x3f7bbf35,0xbf0ebec4,0xbf550000,0xbe483f6d,0x3f7bbf35,0xbf0ebec4,0xbf0e3f80,0x3f7bbec4,0xbe48bf35,0xbf553f6d,
0xbf0e3f80,0x3f7bbec4,0xbe48bf35,0xbf553f6d,0x3f558000,0x3e48bf6d,0xbf7b3f35,0x3f0e3ec4,0x3f550000,0x3e48bf6d,0xbf7b3f35,0x3f0e3ec4,
0x3f0ebf80,0xbf7b3ec4,0x3e483f35,0x3f55bf6d,0xbf6d8000,0x3ec43f35,0x3ec4bf80,0xbf6d3f35,0x3ec4bf80,0xbf6d3f35,0x3f6d0000,0xbec4bf35,
0x3f6d8000,0xbec4bf35,0xbec43f80,0x3f6dbf35,0xbec43f80,0x3f6dbf35,0xbf6d0000,0x3ec43f35,0xbf6d8000,0x3ec43f35,0x3ec4bf80,0xbf6d3f35,
0x3ec4bf80,0xbf6d3f35,0x3f6d0000,0xbec4bf35,0x3f6d8000,0xbec4bf35,0xbec43f80,0x3f6dbf35,0xbec43f80,0x3f6dbf35,0xbf6d0000,0x3ec43f35,
0x3f7b0000,0xbf55bec4,0x3f0e3f35,0xbe48bf6d,0x3e48bf80,0xbf0e3f6d,0x3f55bf35,0xbf7b3ec4,0x3e48bf80,0xbf0e3f6d,0x3f55bf35,0xbf7b3ec4,
0xbf7b8000,0x3f553ec4,0xbf0ebf35,0x3e483f6d,0xbf7b0000,0x3f553ec4,0xbf0ebf35,0x3e483f6d,0xbe483f80,0x3f0ebf6d,0xbf553f35,0x3f7bbec4,
0xbe483f80,0x3f0ebf6d,0xbf553f35,0x3f7bbec4,0x3f7b8000,0xbf55bec4,0x3f0e3f35,0xbe48bf6d,0x3f80,0xbf80,0x3f80,0xbf80,
0xbf800000,0x3f800000,0xbf800000,0x3f800000,0x3f80,0xbf80,0x3f80,0xbf80,0xbf800000,0x3f800000,0xbf800000,0x3f800000,
0x3f80,0xbf80,0x3f80,0xbf80,0xbf800000,0x3f800000,0xbf800000,0x3f800000,0x3f80,0xbf80,0x3f80,0xbf80,
0xbf800000,0x3f800000,0xbf800000,0x3f800000,0xbf7b0000,0x3f55bec4,0xbf0e3f35,0x3e48bf6d,0x3e483f80,0xbf0ebf6d,0x3f553f35,0xbf7bbec4,
0x3e483f80,0xbf0ebf6d,0x3f553f35,0xbf7bbec4,0x3f7b0000,0xbf553ec4,0x3f0ebf35,0xbe483f6d,0x3f7b0000,0xbf553ec4,0x3f0ebf35,0xbe483f6d,
0xbe48bf80,0x3f0e3f6d,0xbf55bf35,0x3f7b3ec4,0xbe48bf80,0x3f0e3f6d,0xbf55bf35,0x3f7b3ec4,0xbf7b0000,0x3f55bec4,0xbf0e3f35,0x3e48bf6d,
0xbec4bf80,0x3f6d3f35,0xbf6d0000,0x3ec4bf35,0x3f6d0000,0xbec43f35,0xbec4bf80,0x3f6d3f35,0x3ec43f80,0xbf6dbf35,0x3f6d0000,0xbec43f35,
0xbf6d0000,0x3ec4bf35,0x3ec43f80,0xbf6dbf35,0xbec4bf80,0x3f6d3f35,0xbf6d0000,0x3ec4bf35,0x3f6d0000,0xbec43f35,0xbec4bf80,0x3f6d3f35,
0x3ec43f80,0xbf6dbf35,0x3f6d0000,0xbec43f35,0xbf6d0000,0x3ec4bf35,0x3ec43f80,0xbf6dbf35,0xbf0ebf80,0x3f7b3ec4,0xbe483f35,0xbf55bf6d,
0xbf550000,0xbe48bf6d,0x3f7b3f35,0xbf0e3ec4,0xbf550000,0xbe48bf6d,0x3f7b3f35,0xbf0e3ec4,0x3f0e3f80,0xbf7bbec4,0x3e48bf35,0x3f553f6d,
0x3f0e3f80,0xbf7bbec4,0x3e48bf35,0x3f553f6d,0x3f550000,0x3e483f6d,0xbf7bbf35,0x3f0ebec4,0x3f550000,0x3e483f6d,0xbf7bbf35,0x3f0ebec4,
0xbf0ebf80,0x3f7b3ec4,0xbe483f35,0xbf55bf6d,0x3f353f80,0xbf350000,0xbf35bf80,0x3f350000,0xbf350000,0xbf35bf80,0x3f350000,0x3f353f80,
0x3f353f80,0xbf350000,0xbf35bf80,0x3f350000,0xbf350000,0xbf35bf80,0x3f350000,0x3f353f80,0x3f353f80,0xbf350000,0xbf35bf80,0x3f350000,
0xbf350000,0xbf35bf80,0x3f350000,0x3f353f80,0x3f353f80,0xbf350000,0xbf35bf80,0x3f350000,0xbf350000,0xbf35bf80,0x3f350000,0x3f353f80,
0x3f0e0000,0x3f7b3f6d,0x3e483f35,0xbf55bec4,0xbf55bf80,0x3e48bec4,0x3f7b3f35,0x3f0e3f6d,0xbf55bf80,0x3e48bec4,0x3f7b3f35,0x3f0e3f6d,
0xbf0e0000,0xbf7bbf6d,0xbe48bf35,0x3f553ec4,0xbf0e0000,0xbf7bbf6d,0xbe48bf35,0x3f553ec4,0x3f553f80,0xbe483ec4,0xbf7bbf35,0xbf0ebf6d,
0x3f553f80,0xbe483ec4,0xbf7bbf35,0xbf0ebf6d,0x3f0e0000,0x3f7b3f6d,0x3e483f35,0xbf55bec4,0xbf6dbf80,0xbec4bf35,0x3ec40000,0x3f6d3f35,
0x3ec40000,0x3f6d3f35,0x3f6d3f80,0x3ec43f35,0x3f6d3f80,0x3ec43f35,0xbec40000,0xbf6dbf35,0xbec40000,0xbf6dbf35,0xbf6dbf80,0xbec4bf35,
0xbf6dbf80,0xbec4bf35,0x3ec40000,0x3f6d3f35,0x3ec40000,0x3f6d3f35,0x3f6d3f80,0x3ec43f35,0x3f6d3f80,0x3ec43f35,0xbec40000,0xbf6dbf35,
0xbec40000,0xbf6dbf35,0xbf6dbf80,0xbec4bf35,0x3f7b3f80,0x3f553f6d,0x3f0e3f35,0x3e483ec4,0x3e480000,0x3f0e3ec4,0x3f553f35,0x3f7b3f6d,
0x3e480000,0x3f0e3ec4,0x3f553f35,0x3f7b3f6d,0xbf7bbf80,0xbf55bf6d,0xbf0ebf35,0xbe48bec4,0xbf7bbf80,0xbf55bf6d,0xbf0ebf35,0xbe48bec4,
0xbe480000,0xbf0ebec4,0xbf55bf35,0xbf7bbf6d,0xbe480000,0xbf0ebec4,0xbf55bf35,0xbf7bbf6d,0x3f7b3f80,0x3f553f6d,0x3f0e3f35,0x3e483ec4,
0x3f808000,0xbf808000,0x3f808000,0xbf808000,0x3f80,0xbf80,0x3f80,0xbf80,0x3f808000,0xbf808000,0x3f808000,0xbf808000,
0x3f80,0xbf80,0x3f80,0xbf80,0x3f808000,0xbf808000,0x3f808000,0xbf808000,0x3f80,0xbf80,0x3f80,0xbf80,
0x3f808000,0xbf808000,0x3f808000,0xbf808000,0x3f80,0xbf80,0x3f80,0xbf80,0x3e483f80,0xbf0ebf6d,0x3f553f35,0xbf7bbec4,
0x3f7b8000,0xbf553ec4,0x3f0ebf35,0xbe483f6d,0x3f7b0000,0xbf553ec4,0x3f0ebf35,0xbe483f6d,0xbe48bf80,0x3f0e3f6d,0xbf55bf35,0x3f7b3ec4,
0xbe48bf80,0x3f0e3f6d,0xbf55bf35,0x3f7b3ec4,0xbf7b8000,0x3f55bec4,0xbf0e3f35,0x3e48bf6d,0xbf7b0000,0x3f55bec4,0xbf0e3f35,0x3e48bf6d,
0x3e483f80,0xbf0ebf6d,0x3f553f35,0xbf7bbec4,0xbf6d8000,0x3ec4bf35,0x3ec43f80,0xbf6dbf35,0xbec4bf80,0x3f6d3f35,0xbf6d0000,0x3ec4bf35,
0x3f6d8000,0xbec43f35,0xbec4bf80,0x3f6d3f35,0x3ec43f80,0xbf6dbf35,0x3f6d0000,0xbec43f35,0xbf6d8000,0x3ec4bf35,0x3ec43f80,0xbf6dbf35,
0xbec4bf80,0x3f6d3f35,0xbf6d0000,0x3ec4bf35,0x3f6d8000,0xbec43f35,0xbec4bf80,0x3f6d3f35,0x3ec43f80,0xbf6dbf35,0x3f6d0000,0xbec43f35,
0xbf550000,0xbe48bf6d,0x3f7b3f35,0xbf0e3ec4,0x3f0e3f80,0xbf7bbec4,0x3e48bf35,0x3f553f6d,0x3f0e3f80,0xbf7bbec4,0x3e48bf35,0x3f553f6d,
0x3f558000,0x3e483f6d,0xbf7bbf35,0x3f0ebec4,0x3f550000,0x3e483f6d,0xbf7bbf35,0x3f0ebec4,0xbf0ebf80,0x3f7b3ec4,0xbe483f35,0xbf55bf6d,
0xbf0ebf80,0x3f7b3ec4,0xbe483f35,0xbf55bf6d,0xbf558000,0xbe48bf6d,0x3f7b3f35,0xbf0e3ec4,0x3f358000,0x3f353f80,0xbf358000,0xbf35bf80,
0x3f353f80,0xbf350000,0xbf35bf80,0x3f350000,0x3f358000,0x3f353f80,0xbf358000,0xbf35bf80,0x3f353f80,0xbf350000,0xbf35bf80,0x3f350000,
0x3f358000,0x3f353f80,0xbf358000,0xbf35bf80,0x3f353f80,0xbf350000,0xbf35bf80,0x3f350000,0x3f358000,0x3f353f80,0xbf358000,0xbf35bf80,
0x3f353f80,0xbf350000,0xbf35bf80,0x3f350000,0xbf55bf80,0x3e48bec4,0x3f7b3f35,0x3f0e3f6d,0xbf0e8000,0xbf7bbf6d,0xbe48bf35,0x3f553ec4,
0xbf0e0000,0xbf7bbf6d,0xbe48bf35,0x3f553ec4,0x3f553f80,0xbe483ec4,0xbf7bbf35,0xbf0ebf6d,0x3f553f80,0xbe483ec4,0xbf7bbf35,0xbf0ebf6d,
0x3f0e8000,0x3f7b3f6d,0x3e483f35,0xbf55bec4,0x3f0e0000,0x3f7b3f6d,0x3e483f35,0xbf55bec4,0xbf55bf80,0x3e48bec4,0x3f7b3f35,0x3f0e3f6d,
0xbec48000,0xbf6dbf35,0xbf6dbf80,0xbec4bf35,0xbf6dbf80,0xbec4bf35,0x3ec40000,0x3f6d3f35,0x3ec48000,0x3f6d3f35,0x3f6d3f80,0x3ec43f35,
0x3f6d3f80,0x3ec43f35,0xbec40000,0xbf6dbf35,0xbec48000,0xbf6dbf35,0xbf6dbf80,0xbec4bf35,0xbf6dbf80,0xbec4bf35,0x3ec40000,0x3f6d3f35,
0x3ec48000,0x3f6d3f35,0x3f6d3f80,0x3ec43f35,0x3f6d3f80,0x3ec43f35,0xbec40000,0xbf6dbf35,0x3e480000,0x3f0e3ec4,0x3f553f35,0x3f7b3f6d,
0xbf7bbf80,0xbf55bf6d,0xbf0ebf35,0xbe48bec4,0xbf7bbf80,0xbf55bf6d,0xbf0ebf35,0xbe48bec4,0xbe488000,0xbf0ebec4,0xbf55bf35,0xbf7bbf6d,
0xbe480000,0xbf0ebec4,0xbf55bf35,0xbf7bbf6d,0x3f7b3f80,0x3f553f6d,0x3f0e3f35,0x3e483ec4,0x3f7b3f80,0x3f553f6d,0x3f0e3f35,0x3e483ec4,
0x3e488000,0x3f0e3ec4,0x3f553f35,0x3f7b3f6d,
};
__device__ __align__(1024) uint8_t g_hT[32 * 262144];
__device__ __align__(1024) bf16 g_U[128 * 2 * 8 * 1024];
__device__ __align__(128) float g_gp[128 * 256];
__device__ __align__(128) uint4 g_agg[16 * 512];
#define CS 32
#define NREP 1
#define NREPH 4
constexpr int RS = 9 * CS;
__device__ __align__(128) unsigned g_cnt[32 * RS];
constexpr int CNT_U = 0, CNT_V = 1, CNT_DONE = 2, CNT_EPOCH = 3, CNT_H = 4  ;
#define PROFK(i) do { } while (0)
#define PROFC(i) do { } while (0)
#define PROF(i) do { } while (0)
#define PROFX(i) do { } while (0)
#define PROFR(i) do { } while (0)
#define PROFT(i) do { } while (0)
#define PROFS(i) do { } while (0)
#define PROFG(i) do { } while (0)

constexpr int SLOT = 32768;
constexpr int OFF_HS = 4 * SLOT;
constexpr int OFF_W = OFF_HS + 16384;
constexpr int OFF_F = OFF_W + 2 * 18432;
constexpr int OFF_G = OFF_F + 8192;
constexpr int OFF_K = OFF_G + 1024;
constexpr int OFF_GW = OFF_K + 2048;
constexpr int OFF_U = 6 * SLOT;
constexpr int OFF_BAR = OFF_U + 32768;
constexpr int OFF_SC = OFF_BAR + 384;
constexpr int OFF_KEPT = OFF_SC + 1024;
constexpr int OFF_PROF = OFF_KEPT + 64;
constexpr int SMEM_BYTES = OFF_PROF;
constexpr int BAR_FULL = 0  , BAR_U = 11, BAR_W = 12  , BAR_F = 14  ,
              BAR_EMPTY = 17  , BAR_HW = 22  , BAR_WR = 25, BAR_VW = 26, BAR_S1 = 27,
              BAR_XC = 28  , BAR_HR = 32,
              BAR_C = 34  , BAR_HD = 36  ;

#define DEVI __device__ __forceinline__
constexpr unsigned SPIN_LIMIT = 1u << 22;

DEVI uint32_t smem_u32(const void* p) { return (uint32_t)__cvta_generic_to_shared(p); }
DEVI uint64_t gtime() { uint64_t t; asm volatile("mov.u64 %0, %%globaltimer;" : "=l"(t)); return t; }
DEVI void mbar_init(uint32_t bar, uint32_t cnt) { asm volatile("mbarrier.init.shared::cta.b64 [%0], %1;" :: "r"(bar), "r"(cnt) : "memory"); }
DEVI void mbar_expect_tx(uint32_t bar, uint32_t bytes) { asm volatile("mbarrier.arrive.expect_tx.shared::cta.b64 _, [%0], %1;" :: "r"(bar), "r"(bytes) : "memory"); }
DEVI void mbar_arrive(uint32_t bar) { asm volatile("mbarrier.arrive.shared::cta.b64 _, [%0];" :: "r"(bar) : "memory"); }
#define WAIT_LOOP "{\n.reg .pred p;\n.reg .u32 n;\nmov.u32 n, 0;\n" \
                  "LW:\nmbarrier.try_wait.parity.shared::cta.b64 p, [%0], %1;\n@p bra LD;\n" \
                  "add.u32 n, n, 1;\nsetp.lt.u32 p, n, 131072;\n@p bra LW;\nLD:\n"
DEVI void mbar_wait(uint32_t bar, uint32_t parity) { asm volatile(WAIT_LOOP "}" :: "r"(bar), "r"(parity) : "memory"); }
DEVI void warp_arrive(uint32_t bar) { asm volatile("{\n.reg .pred p;\nelect.sync _|p, 0xffffffff;\n@p mbarrier.arrive.shared::cta.b64 _, [%0];\n}" :: "r"(bar) : "memory"); }
DEVI bool elect() {
    uint32_t p;
    asm volatile("{\n.reg .pred P;\nelect.sync _|P, 0xffffffff;\nselp.u32 %0, 1, 0, P;\n}" : "=r"(p));
    return p;
}
DEVI void fence_barrier_init() { asm volatile("fence.mbarrier_init.release.cluster;" ::: "memory"); }
DEVI void fence_proxy_async_smem() { asm volatile("fence.proxy.async.shared::cta;" ::: "memory"); }
#define HF 1
#define FPOS 0
DEVI void helper_sync() { asm volatile("bar.sync 1, 128;" ::: "memory"); }

DEVI void pause(unsigned n) {
    asm volatile("{\n.reg .pred p;\n.reg .u32 a, b;\nmov.u32 a, %%clock;\n"
                 "LP:\nmov.u32 b, %%clock;\nsub.u32 b, b, a;\nsetp.lt.u32 p, b, %0;\n@p bra LP;\n}" :: "r"(n) : "memory");
}
DEVI void sched_fence() { asm volatile("{\n.reg .pred p;\n.reg .b32 n;\nLP:\nactivemask.b32 n;\nsetp.eq.u32 p, n, 0;\n@p bra LP;\n}" ::: "memory"); }
#define P_POLL 0
#define NPOLL 1
DEVI void wait_counter(const unsigned* p, unsigned target) {
    unsigned v[NPOLL];
    auto ld = [&](int i) { asm volatile("ld.relaxed.gpu.global.u32 %0, [%1];" : "=r"(v[i]) : "l"(p) : "memory"); };
#pragma unroll
    for (int i = 0; i < NPOLL; i++) { if (i) pause(200); ld(i); }
#pragma unroll 1
    for (unsigned n = 0; n < SPIN_LIMIT; n++) {
#pragma unroll
        for (int i = 0; i < NPOLL; i++) {
            if ((int)(v[i] - target) >= 0) return;
            if (P_POLL) pause(P_POLL);
            ld(i);
        }
    }
}
DEVI void signal_counter(unsigned* p) {
#pragma unroll
    for (int r = 0; r < NREP; r++) asm volatile("red.relaxed.gpu.global.add.u32 [%0], 1;" :: "l"(p + r * RS) : "memory");
}

DEVI void tma_load_3d(uint32_t dst, const CUtensorMap* map, uint32_t bar, int c0, int c1, int c2) {
    asm volatile("cp.async.bulk.tensor.3d.shared::cluster.global.mbarrier::complete_tx::bytes [%0], [%1, {%3, %4, %5}], [%2];"
        :: "r"(dst), "l"(map), "r"(bar), "r"(c0), "r"(c1), "r"(c2) : "memory");
}
DEVI void tma_load_4d(uint32_t dst, const CUtensorMap* map, uint32_t bar, int c0, int c1, int c2, int c3) {
    asm volatile("cp.async.bulk.tensor.4d.shared::cluster.global.mbarrier::complete_tx::bytes [%0], [%1, {%3, %4, %5, %6}], [%2];"
        :: "r"(dst), "l"(map), "r"(bar), "r"(c0), "r"(c1), "r"(c2), "r"(c3) : "memory");
}
DEVI void tma_load_5d(uint32_t dst, const CUtensorMap* map, uint32_t bar, int c0, int c3, int c4) {
    asm volatile("cp.async.bulk.tensor.5d.shared::cluster.global.mbarrier::complete_tx::bytes [%0], [%1, {%3, %6, %6, %4, %5}], [%2];"
        :: "r"(dst), "l"(map), "r"(bar), "r"(c0), "r"(c3), "r"(c4), "r"(0) : "memory");
}
DEVI void tma_store_4d(const CUtensorMap* map, uint32_t src, int c0, int c1, int c2, int c3) {
    asm volatile("cp.async.bulk.tensor.4d.global.shared::cta.bulk_group [%0, {%2, %3, %4, %5}], [%1];"
        :: "l"(map), "r"(src), "r"(c0), "r"(c1), "r"(c2), "r"(c3) : "memory");
}
DEVI void bulk_load(uint32_t dst, const void* src, uint32_t bytes, uint32_t bar) {
    asm volatile("cp.async.bulk.shared::cluster.global.mbarrier::complete_tx::bytes [%0], [%1], %2, [%3];"
        :: "r"(dst), "l"(src), "r"(bytes), "r"(bar) : "memory");
}
DEVI void bulk_prefetch_l2(const void* src, uint32_t bytes) {
    asm volatile("cp.async.bulk.prefetch.L2.global [%0], %1;" :: "l"(src), "r"(bytes) : "memory");
}
DEVI void tma_store_3d(const CUtensorMap* map, uint32_t src, int c0, int c1, int c2) {
    asm volatile("cp.async.bulk.tensor.3d.global.shared::cta.bulk_group [%0, {%2, %3, %4}], [%1];"
        :: "l"(map), "r"(src), "r"(c0), "r"(c1), "r"(c2) : "memory");
}
DEVI void bulk_store(void* dst, uint32_t src, uint32_t bytes) {
    asm volatile("cp.async.bulk.global.shared::cta.bulk_group [%0], [%1], %2;" :: "l"(dst), "r"(src), "r"(bytes) : "memory");
}
DEVI void bulk_commit() { asm volatile("cp.async.bulk.commit_group;" ::: "memory"); }
DEVI void bulk_wait0() { asm volatile("cp.async.bulk.wait_group 0;" ::: "memory"); }

DEVI void wgmma_fence() { asm volatile("wgmma.fence.sync.aligned;" ::: "memory"); }
DEVI void wgmma_commit() { asm volatile("wgmma.commit_group.sync.aligned;" ::: "memory"); }
template<int N> DEVI void wgmma_wait() { asm volatile("wgmma.wait_group.sync.aligned %0;" :: "n"(N) : "memory"); }
template<int N> DEVI void wgmma_wait_all(float (&d)[N]) {
    wgmma_wait<0>();
#pragma unroll
    for (int i = 0; i < N; i++) asm volatile("" : "+f"(d[i]) :: "memory");
}
template<int R> DEVI void reg_alloc() { asm volatile("setmaxnreg.inc.sync.aligned.u32 %0;" :: "n"(R)); }
template<int R> DEVI void reg_dealloc() { asm volatile("setmaxnreg.dec.sync.aligned.u32 %0;" :: "n"(R)); }

constexpr uint32_t SB0 = 1024;
DEVI uint64_t make_desc(uint32_t off, uint32_t lbo, uint32_t sbo, uint32_t mode = 1) {
    return (uint64_t)(((SB0 + off) >> 4) | ((lbo >> 4) << 16)) | ((uint64_t)((sbo >> 4) | (mode << 30)) << 32);
}

#define ACC8(a, o) "+f"(a[o+0]), "+f"(a[o+1]), "+f"(a[o+2]), "+f"(a[o+3]), "+f"(a[o+4]), "+f"(a[o+5]), "+f"(a[o+6]), "+f"(a[o+7])
#define OUT8(a, o) "=f"(a[o+0]), "=f"(a[o+1]), "=f"(a[o+2]), "=f"(a[o+3]), "=f"(a[o+4]), "=f"(a[o+5]), "=f"(a[o+6]), "=f"(a[o+7])
#define ACC32(a, o) ACC8(a, o), ACC8(a, o+8), ACC8(a, o+16), ACC8(a, o+24)

#define SS_N128 "{\n.reg .pred p;\nsetp.ne.b32 p, %66, 0;\n" \
        "wgmma.mma_async.sync.aligned.m64n128k16.f32.bf16.bf16 " \
        "{%0, %1, %2, %3, %4, %5, %6, %7, %8, %9, %10, %11, %12, %13, %14, %15, " \
        "%16, %17, %18, %19, %20, %21, %22, %23, %24, %25, %26, %27, %28, %29, %30, %31, " \
        "%32, %33, %34, %35, %36, %37, %38, %39, %40, %41, %42, %43, %44, %45, %46, %47, " \
        "%48, %49, %50, %51, %52, %53, %54, %55, %56, %57, %58, %59, %60, %61, %62, %63}, " \
        "%64, %65, p, 1, 1, %67, %68;\n}\n"
template<int TA, int TB>
DEVI void wgmma_n128(float (&d)[64], uint64_t da, uint64_t db, int scale_d) {
    asm volatile(SS_N128 : ACC32(d, 0), ACC32(d, 32) : "l"(da), "l"(db), "r"(scale_d), "n"(TA), "n"(TB));
}
DEVI void wgmma_n128_set(float (&d)[64], uint64_t da, uint64_t db) {
    asm volatile(SS_N128 : OUT8(d, 0), OUT8(d, 8), OUT8(d, 16), OUT8(d, 24), OUT8(d, 32), OUT8(d, 40), OUT8(d, 48), OUT8(d, 56) : "l"(da), "l"(db), "n"(0), "n"(0), "n"(1));
}
#define SS_N16 "{\n.reg .pred p;\nsetp.ne.b32 p, 0, 0;\n" \
        "wgmma.mma_async.sync.aligned.m64n16k16.f32.bf16.bf16 " \
        "{%0, %1, %2, %3, %4, %5, %6, %7}, %8, %9, p, 1, 1, %10, 0;\n}\n"
template<int TA> DEVI void wgmma_n16(float* d, uint64_t da, uint64_t db) {
    asm volatile(SS_N16 : OUT8(d, 0) : "l"(da), "l"(db), "n"(TA));
}
#define SS_N8 "{\n.reg .pred p;\nsetp.ne.b32 p, %6, 0;\n" \
        "wgmma.mma_async.sync.aligned.m64n8k16.f32.bf16.bf16 {%0, %1, %2, %3}, %4, %5, p, 1, 1, 0, 0;\n}\n"
DEVI void wgmma_n8(float (&d)[4], uint64_t da, uint64_t db, bool add) {
    if (add) asm volatile(SS_N8 : "+f"(d[0]), "+f"(d[1]), "+f"(d[2]), "+f"(d[3]) : "l"(da), "l"(db), "n"(1));
    else asm volatile(SS_N8 : "=f"(d[0]), "=f"(d[1]), "=f"(d[2]), "=f"(d[3]) : "l"(da), "l"(db), "n"(0));
}
#define RS_N64 "{\n.reg .pred p;\nsetp.ne.b32 p, %37, 0;\n" \
        "wgmma.mma_async.sync.aligned.m64n64k16.f32.bf16.bf16 " \
        "{%0, %1, %2, %3, %4, %5, %6, %7, %8, %9, %10, %11, %12, %13, %14, %15, " \
        "%16, %17, %18, %19, %20, %21, %22, %23, %24, %25, %26, %27, %28, %29, %30, %31}, " \
        "{%32, %33, %34, %35}, %36, p, 1, 1, %38;\n}\n"
template<int SCALE_D, int TB = 0>
DEVI void wgmma_rs_n64(float (&d)[32], const uint32_t (&a)[4], uint64_t db) {
    if (SCALE_D) asm volatile(RS_N64 : ACC32(d, 0) : "r"(a[0]), "r"(a[1]), "r"(a[2]), "r"(a[3]), "l"(db), "n"(1), "n"(TB));
    else asm volatile(RS_N64 : OUT8(d, 0), OUT8(d, 8), OUT8(d, 16), OUT8(d, 24) : "r"(a[0]), "r"(a[1]), "r"(a[2]), "r"(a[3]), "l"(db), "n"(0), "n"(TB));
}
#define SS_N64 "{\n.reg .pred p;\nsetp.ne.b32 p, %34, 0;\n" \
        "wgmma.mma_async.sync.aligned.m64n64k16.f32.bf16.bf16 " \
        "{%0, %1, %2, %3, %4, %5, %6, %7, %8, %9, %10, %11, %12, %13, %14, %15, " \
        "%16, %17, %18, %19, %20, %21, %22, %23, %24, %25, %26, %27, %28, %29, %30, %31}, " \
        "%32, %33, p, 1, 1, 0, 1;\n}\n"
template<int SCALE_D> DEVI void wgmma_ss_n64(float (&d)[32], uint64_t da, uint64_t db) {
    if (SCALE_D) asm volatile(SS_N64 : ACC32(d, 0) : "l"(da), "l"(db), "n"(1));
    else asm volatile(SS_N64 : OUT8(d, 0), OUT8(d, 8), OUT8(d, 16), OUT8(d, 24) : "l"(da), "l"(db), "n"(0));
}
DEVI void ldsm_x4_t(uint32_t (&r)[4], uint32_t addr) {
    asm volatile("ldmatrix.sync.aligned.m8n8.x4.trans.shared.b16 {%0, %1, %2, %3}, [%4];"
        : "=r"(r[0]), "=r"(r[1]), "=r"(r[2]), "=r"(r[3]) : "r"(addr) : "memory");
}
DEVI void ldsm_x4(uint32_t (&r)[4], uint32_t addr) {
    asm volatile("ldmatrix.sync.aligned.m8n8.x4.shared.b16 {%0, %1, %2, %3}, [%4];"
        : "=r"(r[0]), "=r"(r[1]), "=r"(r[2]), "=r"(r[3]) : "r"(addr) : "memory");
}
DEVI void stsm_x4(uint32_t addr, uint32_t r0, uint32_t r1, uint32_t r2, uint32_t r3) {
    asm volatile("stmatrix.sync.aligned.m8n8.x4.shared.b16 [%0], {%1, %2, %3, %4};"
        :: "r"(addr), "r"(r0), "r"(r1), "r"(r2), "r"(r3) : "memory");
}
DEVI void stsm_x4_t(uint32_t addr, uint32_t r0, uint32_t r1, uint32_t r2, uint32_t r3) {
    asm volatile("stmatrix.sync.aligned.m8n8.x4.trans.shared.b16 [%0], {%1, %2, %3, %4};"
        :: "r"(addr), "r"(r0), "r"(r1), "r"(r2), "r"(r3) : "memory");
}
DEVI uint32_t movm(uint32_t a) { uint32_t d; asm volatile("movmatrix.sync.aligned.m8n8.trans.b16 %0, %1;" : "=r"(d) : "r"(a)); return d; }
DEVI uint32_t pack2(float lo, float hi) { uint32_t d; asm("cvt.rn.bf16x2.f32 %0, %1, %2;" : "=r"(d) : "f"(hi), "f"(lo)); return d; }
DEVI float bf_lo(uint32_t v) { return __uint_as_float(v << 16); }
DEVI float bf_hi(uint32_t v) { return __uint_as_float(v & 0xffff0000u); }
DEVI float bf_round(float v) { return __bfloat162float(__float2bfloat16_rn(v)); }
DEVI uint32_t bf_mul2(uint32_t a, uint32_t b) { uint32_t d; asm("mul.rn.bf16x2 %0, %1, %2;" : "=r"(d) : "r"(a), "r"(b)); return d; }
DEVI uint32_t bf_add2(uint32_t a, uint32_t b) { uint32_t d; asm("add.rn.bf16x2 %0, %1, %2;" : "=r"(d) : "r"(a), "r"(b)); return d; }
DEVI uint32_t bf_sub2(uint32_t a, uint32_t b) { uint32_t d; asm("sub.rn.bf16x2 %0, %1, %2;" : "=r"(d) : "r"(a), "r"(b)); return d; }
DEVI uint4 lds128u(uint32_t a) { uint4 v; asm volatile("ld.shared.v4.u32 {%0, %1, %2, %3}, [%4];" : "=r"(v.x), "=r"(v.y), "=r"(v.z), "=r"(v.w) : "r"(a) : "memory"); return v; }
DEVI void sts128u(uint32_t a, uint32_t x, uint32_t y, uint32_t z, uint32_t w) { asm volatile("st.shared.v4.u32 [%0], {%1, %2, %3, %4};" :: "r"(a), "r"(x), "r"(y), "r"(z), "r"(w) : "memory"); }
DEVI uint2 lds64u(uint32_t a) { uint2 v; asm volatile("ld.shared.v2.u32 {%0, %1}, [%2];" : "=r"(v.x), "=r"(v.y) : "r"(a) : "memory"); return v; }
DEVI uint32_t ldg32u(const void* p) { uint32_t v; asm volatile("ld.global.nc.u32 %0, [%1];" : "=r"(v) : "l"(p) : "memory"); return v; }
DEVI void sts64(uint32_t a, float x, float y) { asm volatile("st.shared.v2.f32 [%0], {%1, %2};" :: "r"(a), "f"(x), "f"(y) : "memory"); }
DEVI void sts32(uint32_t a, uint32_t v) { asm volatile("st.shared.u32 [%0], %1;" :: "r"(a), "r"(v) : "memory"); }
DEVI uint32_t lds16(uint32_t a) { uint32_t v; asm volatile("ld.shared.u16 %0, [%1];" : "=r"(v) : "r"(a) : "memory"); return v; }
DEVI void cmul2(uint32_t& x, uint32_t& y, uint32_t c, uint32_t s, uint32_t n) {
    asm("{\n.reg .b32 t, u;\nmul.rn.bf16x2 t, %1, %4;\nmul.rn.bf16x2 u, %1, %2;\n"
        "fma.rn.bf16x2 %1, %0, %3, u;\nfma.rn.bf16x2 %0, %0, %2, t;\n}" : "+r"(x), "+r"(y) : "r"(c), "r"(s), "r"(n));
}
DEVI uint32_t neg2(uint32_t s) { uint32_t n; asm volatile("xor.b32 %0, %1, 0x80008000;" : "=r"(n) : "r"(s)); return n; }
DEVI void cmul2(uint32_t& x, uint32_t& y, uint32_t c, uint32_t s) { cmul2(x, y, c, s, neg2(s)); }
DEVI void cmul2c(uint32_t& x, uint32_t& y, uint32_t c, uint32_t s) { cmul2(x, y, c, neg2(s), s); }
DEVI void sts16(uint32_t a, float v) { asm volatile("st.shared.u16 [%0], %1;" :: "r"(a), "r"(pack2(v, v)) : "memory"); }

DEVI float2 cmul(float2 a, float2 b) { return make_float2(fmaf(a.x, b.x, -a.y * b.y), fmaf(a.x, b.y, a.y * b.x)); }
DEVI float2 cfma(float2 a, float2 b, float2 c) { return make_float2(fmaf(a.x, b.x, fmaf(-a.y, b.y, c.x)), fmaf(a.x, b.y, fmaf(a.y, b.x, c.y))); }

DEVI float2 csq(float2 a) {
    float y;
    asm("{\n.reg .f32 t;\nmul.ftz.f32 t, %1, %2;\nmul.ftz.f32 %0, t, 0f40000000;\n}" : "=f"(y) : "f"(a.x), "f"(a.y));
    return make_float2(fmaf(a.x, a.x, -a.y * a.y), y);
}

struct Params {
    const bf16 *lam_re, *lam_im, *log_dt, *dskip, *gate_w, *c_re, *c_im, *b_re, *b_im, *x;
    int swapB;
    int2 tile[130];
};

#define P_W0 0
#define P_W1 0
#define P_R8F 0
#define P_R8I 0
#define P_CF 0
#define P_S1 0
#define P_SK 0
#define R8_POLL 8
#define R8B 1
#define SCB 32
#define C0 1
#define R8A 4
DEVI void radix8(uint32_t sb, bool inv, int w, int lane, int bar) {
    const uint64_t dg = make_desc(OFF_G + (inv ? 512 : 0), 128, 256, 0), da = make_desc(OFF_U, 16, 16384);
    float acc[2][64];
    wgmma_fence();
#pragma unroll
    for (int j = 0; j < 8; j++) wgmma_n16<1>(acc[0] + 8 * j, da + 64 * j, dg);
    wgmma_commit();
    sched_fence();
    asm volatile("" : "+r"(lane));
    const int kk = lane & 7, ch = 2 * w + ((lane >> 3) & 1);
    const uint32_t st = sb + OFF_U + (inv ? (lane >> 4) * 16384 + kk * 128 + ((ch ^ kk) << 4)
        : (kk & 1) * 16384 + (kk >> 2) * 2048 + (lane >> 4) * 1024 + (w >> 1) * 128 + ((((kk & 2) * 2 + ((ch & 3) ^ (kk >> 2) ^ (2 * (kk & 1)))) ^ (w >> 1)) << 4));
    uint32_t sa[4];
#pragma unroll
    for (int i = 0; i < 4; i++) { sa[i] = inv ? (st ^ (i << 4)) + i * 1024 : (st ^ (i << 5)) + i * 256; asm volatile("" : "+r"(sa[i])); }
    const int warp = inv;
    sched_fence();
    if (R8A) {
        wgmma_fence();
#pragma unroll
        for (int j = 0; j < R8A; j++) wgmma_n16<1>(acc[1] + 8 * j, da + 64 * (8 + j), dg);
        wgmma_commit();
    }
    PROFC(8);
#pragma unroll
    for (int i = 0; i < 2; i++) {
        if (i || !R8A) wgmma_wait<0>(); else wgmma_wait<1>();
#pragma unroll
        for (int j = 0; j < 64; j++) asm volatile("" : "+f"(acc[i][j]) :: "memory");
        PROFC(9 + 2 * i);
        asm volatile("bar.sync %0, 128;" :: "r"(bar) : "memory");
        if (!i && R8A < 8) wgmma_fence();
#pragma unroll
        for (int j = 0; j < 8; j++) {
            const float* a = acc[i] + 8 * j;
            if (!i && j + R8A < 8) wgmma_n16<1>(acc[1] + 8 * (j + R8A), da + 64 * (8 + j + R8A), dg);
            stsm_x4_t(sa[j & 3] + (2 * i + (j >> 2)) * 4096, pack2(a[0], a[1]), pack2(a[2], a[3]), pack2(a[4], a[5]), pack2(a[6], a[7]));
            if ((P_R8F || P_R8I) && (j & 1) && j < 7 && (i || j + R8A >= 7)) pause(inv ? P_R8I : P_R8F);
        }
        if (!i && R8A < 8) wgmma_commit();
        PROFC(10 + 2 * i);
        if (i ? inv || !(FPOS & 1) : inv && HF) fence_proxy_async_smem();
        __syncwarp();
        if (inv) warp_arrive(sb + OFF_BAR + 8 * BAR_VW);
    }
}

template<int N> DEVI void c_take(float (&acc)[32], uint32_t (&p)[16]) {
    wgmma_wait<N>();
#pragma unroll
    for (int i = 0; i < 32; i++) asm volatile("" : "+f"(acc[i]) :: "memory");
#pragma unroll
    for (int i = 0; i < 16; i++) p[i] = pack2(acc[2 * i], acc[2 * i + 1]);
}
DEVI uint64_t desc_at(uint64_t d, uint32_t o) { return (d & 0xffffffff00000000ull) | ((uint32_t)d + o); }
DEVI void c_cols(float (&acc)[32], uint64_t df, uint64_t db, int o) {
    wgmma_fence();
    wgmma_ss_n64<0>(acc, df, desc_at(db, o));
#pragma unroll
    for (int s = 1; s < 4; s++) wgmma_ss_n64<1>(acc, df + 2 * s, desc_at(db, o + 256 * s));
    wgmma_commit();
}

DEVI void phase_c(uint32_t sb, int ps, bool rot, int w, int lane) {
    const int warp = ps, bar = 5 + ps;
    PROFC(0);
    const uint32_t rb = sb + OFF_U + ps * 16384;
    const uint64_t df = make_desc(OFF_F, 16, 1024), db = make_desc(OFF_U + ps * 16384, 16, 1024);
    float acc[2][32];
    c_cols(acc[0], df, db, 0);
    c_cols(acc[1], df, db, 128);
    sched_fence();
    asm volatile("" : "+r"(lane));
    const int g = lane & 7, l3 = (lane >> 3) & 1, l4 = lane >> 4;
    uint32_t wf[2][4][4];
    const uint32_t wo = sb + OFF_W + (1 - ps) * 18432 + l4 * 9216 + g * 64 + ((w ^ (g >> 1)) << 4);
    uint32_t wd = wo + l3 * 1152, wm[2] = {wo + 4608 + (((rot ? 4 : 3) - l3) & 3) * 1152, wo + 4608 + ((rot ? 2 : 1) - l3) * 1152};
    uint32_t xa = rb + w * 4096 + l4 * 1024 + g * 128 + (((4 * l3) ^ g) << 4);
    uint32_t oa = rb + (4 * w + (g >> 1)) * 1024 + (1 - l3) * 512 + (((4 * (g & 1) + l4) ^ (4 - 4 * l3) ^ (g >> 1)) << 4);
    auto load_w = [&](int h) {
#pragma unroll
        for (int j = 0; j < 4; j++) ldsm_x4_t(wf[h][j], (j < 2 ? wd + h * 2304 : wm[h]) + (j & 1) * 512);
    };
    uint32_t tw[8][3];
    {
        const float a0 = (float)(8 * w + (lane >> 2)) * 0.0061359231515425649f, q2 = (float)(2 * (lane & 3)), p16 = (float)(16 * ps);
        const float b0 = a0 * (q2 + p16), b1 = a0 * (q2 - p16);
#pragma unroll
        for (int j = 0; j < 4; j++) {
            const float u = fmaf(a0, 8.f * j, j < 2 ? b0 : b1), v = u + a0, su = __sinf(u), sv = __sinf(v);
            tw[j][0] = pack2(__cosf(u), __cosf(v)); tw[j][1] = pack2(-su, -sv); tw[j][2] = pack2(su, sv);
        }
    }
#pragma unroll
    for (int j = 0; j < 4; j++) asm volatile("" : "+r"(tw[j][0]), "+r"(tw[j][1]), "+r"(tw[j][2]));
    asm volatile("" : "+r"(wd), "+r"(wm[0]), "+r"(wm[1]), "+r"(xa), "+r"(oa));
    sched_fence();
    auto twiddle = [&](uint32_t& x, uint32_t& y, int j) { cmul2(x, y, tw[j][0], tw[j][1], tw[j][2]); };
#pragma unroll
    for (int h = 0; h < 2; h++) {
        uint32_t p[16], a[4][4];
        c_take<1>(acc[h], p);
        if (h == 0) PROFC(1);
#pragma unroll
        for (int i = 0; i < 8; i++) {
            twiddle(p[2 * i], p[2 * i + 1], (i & 3) ^ h);
            a[(i & 3) ^ h][i >> 2] = p[2 * i];
            a[(i & 3) ^ h][2 + (i >> 2)] = p[2 * i + 1];
        }
        wgmma_fence();
        wgmma_rs_n64<0>(acc[h], a[0], desc_at(df, 4 * ps));
        wgmma_rs_n64<1>(acc[h], a[1], desc_at(df, 4 * ps + 2));
        wgmma_rs_n64<1>(acc[h], a[2], desc_at(df, 4 - 4 * ps));
        wgmma_rs_n64<1>(acc[h], a[3], desc_at(df, 6 - 4 * ps));
        wgmma_commit();
        load_w(h);
    }
    PROFC(2);
#pragma unroll
    for (int h = 0; h < 2; h++) {
        uint32_t p[16], a[4][4];
        c_take<1>(acc[h], p);
#pragma unroll
        for (int i = 0; i < 8; i++) {
            const int j = i >> 1, r = i & 1;
            if (j < 2) cmul2(p[4 * j + r], p[4 * j + 2 + r], wf[h][j][r], wf[h][j][2 + r]);
            else cmul2c(p[4 * j + r], p[4 * j + 2 + r], wf[h][j][r], wf[h][j][2 + r]);
            a[j][r] = p[4 * j + 2 + r];
            a[j][2 + r] = p[4 * j + r];
        }
        wgmma_fence();
        wgmma_rs_n64<0>(acc[h], a[0], df);
#pragma unroll
        for (int j = 1; j < 4; j++) wgmma_rs_n64<1>(acc[h], a[j], df + 2 * j);
        wgmma_commit();
    }
    PROFC(3);
#pragma unroll
    for (int j = 0; j < 12; j++) tw[4 + j / 3][j % 3] = ps ? tw[(j / 3) ^ 2][j % 3] : tw[j / 3][j % 3];
    uint32_t p[16];
    auto put = [&](int h) {
#pragma unroll
        for (int i = 0; i < 8; i++) twiddle(p[4 * (i >> 1) + (i & 1)], p[4 * (i >> 1) + 2 + (i & 1)], 4 + (i >> 1));
        if (!h) {
#pragma unroll
            for (int i = 0; i < 16; i++) asm volatile("" : "+r"(p[i]) :: "memory");
            asm volatile("bar.sync %0, 128;" :: "r"(bar) : "memory");
        }
#pragma unroll
        for (int j = 0; j < 4; j++) stsm_x4((xa ^ (j << 4)) + h * 2048, p[4 * j], p[4 * j + 1], p[4 * j + 2], p[4 * j + 3]);
        if (h && ps && !(FPOS & 2)) fence_proxy_async_smem();
    };
    c_take<1>(acc[0], p);
    put(0);
    c_take<0>(acc[1], p);
    if (!ps) put(1);
    else {
        float fin[2][64];
        auto cols = [&](int n) {
            wgmma_fence();
            wgmma_n128_set(fin[n], df, make_desc(OFF_U + n * 16384, 2048, 1024));
#pragma unroll
            for (int s = 1; s < 4; s++) wgmma_n128<0, 1>(fin[n], df + 2 * s, make_desc(OFF_U + n * 16384, 2048, 1024) + 256 * s, 1);
            wgmma_commit();
            sched_fence();
        };
        cols(0);
#pragma unroll
        for (int i = 0; i < 16; i++) asm volatile("" : "+r"(p[i]) :: "memory");
        put(1);
        PROFC(4);
#pragma unroll
        for (int n = 0; n < 2; n++) {
            wgmma_wait_all(fin[n]);
            asm volatile("bar.sync 6, 128;" ::: "memory");
            if (!n && (FPOS & 2)) fence_proxy_async_smem();
            if (!n) cols(1);
#pragma unroll
            for (int i = 0; i < 8; i++) {
                const int r = i >> 1;
                const float* a = fin[n] + 8 * i;
                stsm_x4((oa ^ ((r ^ (2 * (i & 1))) << 4)) + r * 128 + (n - 1) * 16384, pack2(a[0], a[1]), pack2(a[2], a[3]), pack2(a[4], a[5]), pack2(a[6], a[7]));
                if (P_CF && (i & 1) && i < 7) pause(P_CF);
            }
        }
        if (!(FPOS & 4)) fence_proxy_async_smem();
        asm volatile("bar.sync 6, 128;" ::: "memory");
        if (FPOS & 4) fence_proxy_async_smem();
    }
    PROFC(5);
}

#define P_T 60
#define P_C 300
#define PACE_HA 100
#define PACE_HB 0
#define HN 4
#define PACE_V 100
#define VFIRST 4
#define K0 2
#define P_K 0
#define NB0 2
#define VK 63
#define LEAD 1
#define K_XE 56
#define PACE_H 200
#define T_W0 1600
#define T_XS 1600
#define D_XS 0
#define P_XS 400
#define T_G 0
#define T_BA 400
#define T_W1 3000
#define P_W 0
#define P_XE 600
#define P_R0 0
#define P_CAR 300
#define HWZ 2
#define R_REL 1
#define R_MID 4
#define W_EARLY 0
#define SEP 0
#define UN 1
#define FA0 16
#define P_CARB 200
#define D_CAR 20
#define HPOLL 1
#define P_HP 0
#define PF0 0
#define NPF 1
#define PFM 63
#define PFT 0
#define T_PFT 0
#define N_T 1
#define HS0 3
#define T_B2 4000
#define T_W 4500
#define PACE_U 200
#define PACE_L 0
#define T_FA 0
#define REG_M 216
#define REG_H 72
#define NS 4
#define QM1 42
#define QM2 36
#define SLOT_OF(k) (((k) + 1) % 4)
DEVI void tma_prefetch_4d(const CUtensorMap* map, int c0, int c1, int c2, int c3) {
    asm volatile("cp.async.bulk.prefetch.tensor.4d.L2.global [%0, {%1, %2, %3, %4}];" :: "l"(map), "r"(c0), "r"(c1), "r"(c2), "r"(c3) : "memory");
}
DEVI void bar_sync(int id, int n) { asm volatile("bar.sync %0, %1;" :: "r"(id), "r"(n) : "memory"); }
DEVI void bar_arrive(int id, int n) { asm volatile("bar.arrive %0, %1;" :: "r"(id), "r"(n) : "memory"); }
DEVI uint4 ldg128(const void* p) { uint4 v; asm volatile("ld.global.nc.v4.u32 {%0, %1, %2, %3}, [%4];" : "=r"(v.x), "=r"(v.y), "=r"(v.z), "=r"(v.w) : "l"(p)); return v; }
DEVI uint32_t ldg16(const void* p) { uint32_t v; asm volatile("ld.global.nc.u16 %0, [%1];" : "=r"(v) : "l"(p)); return v; }
DEVI uint32_t bf_fma2(uint32_t a, uint32_t b, uint32_t c) { uint32_t d; asm("fma.rn.bf16x2 %0, %1, %2, %3;" : "=r"(d) : "r"(a), "r"(b), "r"(c)); return d; }
DEVI uint32_t lo2(uint32_t a) { uint32_t d; asm("{\n.reg .b16 l, h;\nmov.b32 {l, h}, %1;\nmov.b32 %0, {l, l};\n}" : "=r"(d) : "r"(a)); return d; }
DEVI uint32_t hi2(uint32_t a) { uint32_t d; asm("{\n.reg .b16 l, h;\nmov.b32 {l, h}, %1;\nmov.b32 %0, {h, h};\n}" : "=r"(d) : "r"(a)); return d; }
DEVI void bulk_wait_read() { asm volatile("cp.async.bulk.wait_group.read 0;" ::: "memory"); }

DEVI float lds32f(uint32_t a) { float v; asm volatile("ld.shared.f32 %0, [%1];" : "=f"(v) : "r"(a) : "memory"); return v; }
DEVI uint32_t mbar_test(uint32_t bar, uint32_t parity) {
    uint32_t ok;
    asm volatile("{\n.reg .pred p;\nmbarrier.test_wait.parity.shared::cta.b64 p, [%1], %2;\nselp.u32 %0, 1, 0, p;\n}" : "=r"(ok) : "r"(bar), "r"(parity) : "memory");
    return ok;
}
template<int TA> DEVI void ring_steps(float (&acc)[2][64], uint32_t sb, uint32_t fb, int n, int ns, int s, uint32_t ph, int first_bar, int last_bar, int pi) {
    const uint64_t da0 = TA ? make_desc(0, 2048, 256, 3) : make_desc(0, 16, 1024), db0 = make_desc(16384, 16, 1024);
    const uint32_t fe = fb + 8 * ns, de = sb + OFF_BAR + 8 * BAR_EMPTY - fb;
    uint32_t eb = sb + OFF_BAR + 8 * BAR_HR, f = fb + 8 * s;
    uint64_t da = da0 + (uint32_t)(s * 2048), db = db0 + (uint32_t)(s * 2048);
    bool first = true;
    if (TA) PROFT(72); else if (threadIdx.x == 0) PROFX(93);
    mbar_wait(f, ph);
    if (TA) PROFT(73);
    if (first_bar) bar_sync(first_bar, 256);
    if (TA) PROFT(74);
#pragma unroll 1
    for (;;) {
        PROFK(pi++);
        wgmma_fence();
        constexpr int QM = TA ? QM2 : QM1;
#pragma unroll
        for (int j = 0; j < 8; j++) {
            wgmma_n128<TA, 0>(acc[j & 1], da + 512 * (j & 1) + (TA ? 32 : 2) * (j >> 1), db + 2 * (j >> 1), j > 1 || !first);
            if ((QM >> j) & 1) {
                wgmma_commit();
                wgmma_wait<1>();
                if (!(QM & ((1 << j) - 1))) warp_arrive(eb);
                wgmma_fence();
            }
        }
        wgmma_commit();
        first = false;
        --n;
        if (TA && n == 0) break;
        eb = f + de;
        f += 8; da += 2048; db += 2048;
        if (f == fe) { f = fb; da = da0; db = db0; ph ^= 1; }
        const uint32_t ok = mbar_test(f, ph);
        wgmma_wait<1>();
        if (!ok) mbar_wait(f, ph);
        __syncwarp();
        if (!TA && n == 1) break;
    }
    if (!TA) {
        PROFK(pi++);
        wgmma_fence();
#pragma unroll
        for (int j = 0; j < 8; j++) {
            wgmma_n128<TA, 0>(acc[j >> 2], da + 512 * (j >> 2) + 2 * (j & 3), db + 2 * (j & 3), 1);
            if (j == 3) {
                wgmma_commit();
                wgmma_wait<1>();
                warp_arrive(eb);
                wgmma_fence();
            }
        }
        wgmma_commit();
    }
    if (last_bar) bar_arrive(last_bar, 256);
}

__global__ void __cluster_dims__(2, 1, 1) __launch_bounds__(384, 1)
fused_kernel(const __grid_constant__ CUtensorMap mapB, const __grid_constant__ CUtensorMap mapX,
             const __grid_constant__ CUtensorMap mapXs, const __grid_constant__ CUtensorMap mapU0,
             const __grid_constant__ CUtensorMap mapU2, const __grid_constant__ CUtensorMap mapXe,
             const __grid_constant__ CUtensorMap mapCre, const __grid_constant__ CUtensorMap mapCim,
             const __grid_constant__ CUtensorMap mapV, const __grid_constant__ CUtensorMap mapO,
             const __grid_constant__ CUtensorMap mapWr, const __grid_constant__ CUtensorMap mapWi,
             const __grid_constant__ CUtensorMap mapH,
             const __grid_constant__ Params P) {
    extern __shared__ __align__(1024) uint8_t sm[];
    const uint32_t sb = smem_u32(sm);
    const uint32_t bars = sb + OFF_BAR;
    const int tid = threadIdx.x;
    const int2 rc = P.tile[blockIdx.x];
    auto first_loads = [&](int k0, int k1) {
#pragma unroll 1
        for (int k = k0; k < k1; k++) {
            const uint32_t full = bars + 8 * (BAR_FULL + k), st = sb + k * SLOT;
            if (P_K && k1 == 5) pause(P_K);
            if (k1 == 5) mbar_expect_tx(full, SLOT);
            tma_load_4d(st, &mapB, full, k * 64, 0, 0, rc.x);
            tma_load_4d(st + 16384, &mapX, full, k * 64, 0, 0, rc.y);
            if (k1 < 5) mbar_expect_tx(full, SLOT);
            if (k == 0) PROFX(89);
        }
    };
    if ((tid >> 5) == 8 && elect()) {
        PROF(0);
#pragma unroll
        for (int i = 0; i < NB0; i++) mbar_init(bars + 8 * i, 1);
        fence_barrier_init();
        fence_proxy_async_smem();
        PROFX(88);
        if (rc.x >= 0) {
            first_loads(0, 1);
            first_loads(1, K0);
        }
        if (NB0 < 5) {
#pragma unroll
            for (int i = NB0; i < 5; i++) mbar_init(bars + 8 * i, 1);
            fence_barrier_init();
            fence_proxy_async_smem();
        }
    }
    sched_fence();
    const int b = ((unsigned)rc.x >> 24) + ((rc.x & 24) << 2) + ((rc.y >> 3) & 16) + ((rc.x >> 2) & 8) + ((rc.y >> 7) & 6) + ((rc.y >> 6) & 1);
    const bool main_cta = b < 128;
    if (b == 129) return;
    const int warp = __shfl_sync(0xffffffffu, tid >> 5, 0), lane = tid & 31;
    const int rp = (b >> 1) & 3, mq = ((b >> 3) & 2) + (b & 1), dt = ((b >> 1) & 4) + (b >> 5), tc = 4 * rp + mq;
    if (warp >= 8) {
        __syncwarp();
        reg_dealloc<REG_H>();
        if (warp == 8) { bar_arrive(0, 256); bar_arrive(4, 384); }
    }
    if (warp == 8 && elect()) {
        if (main_cta) first_loads(K0, 5);
        PROF(27);
    }
    const int cls = b == 128 ? 128 : (b & 31) ? (b & 31) + 64 * (b >> 5) : (b == 64 ? 32 : b == 32 ? 64 : b);
    if (warp > 3 && warp != 8) {
        if (elect()) {
            if (warp == 11) PROFG(0);
            if ((sb & 0x3FFFF) != SB0) __trap();
#pragma unroll 1
            for (int u = warp - 4 - (warp > 8); u < 11; u += 7) {
                mbar_init(bars + 8 * (5 + u), 1);
                if (!u) mbar_arrive(bars + 8 * (BAR_FULL + 5));
                if (u == 8) sts32(sb + OFF_KEPT + 32, 0);
                mbar_init(bars + 8 * (16 + u), u ? 4 : 1);
                mbar_init(bars + 8 * (27 + u), u < 1 ? 4 : u == 6 ? 8 : (u == 7 || u == 8) ? 64 : 1);
            }
            fence_barrier_init();
            fence_proxy_async_smem();
        }
        __syncwarp();
        bar_arrive(4, 384);
    }
    __syncwarp();
    const bool real_cls = (cls & 127) == 0;
    const int t = tid & 127;
    auto load_epoch = [&]() {
        unsigned e;
        asm volatile("ld.relaxed.gpu.global.u32 %0, [g_cnt + %1];" : "=r"(e) : "n"(CNT_EPOCH * CS * 4));
        return e + 1;
    };
    const int g = lane >> 2, q = lane & 3;

    if (warp < 8) {
        reg_alloc<REG_M>();
        const int wg = warp >> 2, w = warp & 3;
        if (tid == 0) PROFX(94);
        if (tid == 224) PROFG(8);
        auto kept = [&](int i) { uint64_t v; asm volatile("ld.volatile.shared.u64 %0, [%1];" : "=l"(v) : "r"(sb + OFF_KEPT + 8 * i) : "memory"); return v; };
        const uint32_t fb = bars + 8 * (BAR_FULL + 5 * wg);
        if (wg) {
            sched_fence();
            bar_sync(0, 256);
            uint32_t fa[16][4];
            auto load_fa = [&](int i0, int i1) {
#pragma unroll
                for (int i = i0; i < i1; i++)
                    asm volatile("ld.global.nc.L1::no_allocate.v4.u32 {%0, %1, %2, %3}, [%4];" : "=r"(fa[i][0]), "=r"(fa[i][1]), "=r"(fa[i][2]), "=r"(fa[i][3]) : "l"((const uint4*)c_tab + i * 128 + t));
            };
            {
                const int pp = (dt * 64 + 8 * (t & 64) + (t & 63)) & 1023;
                const uint32_t lr_ = ldg16(P.lam_re + pp), li_ = ldg16(P.lam_im + pp), ld_ = ldg16(P.log_dt + pp);
                const unsigned epoch = load_epoch();
                if (T_FA) pause(T_FA);
                load_fa(0, FA0);
                if (t < 64 && main_cta) g_agg[rp * 2048 + (dt + (t >> 5) * 8) * 128 + lane * 4 + mq] = make_uint4(0u, 0u, 0u, 0u);
                if (t < 4) asm volatile("st.shared.u64 [%0], %1;" :: "r"(sb + OFF_KEPT + 8 * lane),
                    "l"(lane == 0 ? (P.swapB ? 0xffffffffull : 0xffffff7full) | ((uint64_t)epoch << 32) : lane == 1 ? (uint64_t)g_agg : (uint64_t)&mapB) : "memory");
                const float lr = bf_lo(lr_), li = bf_lo(li_);
                const float dl = bf_round(expf(bf_lo(ld_)));
                const float mag = expf(dl * lr);
                float sn, cs; sincospif(dl * li * 0.31830988618379067f, &sn, &cs);
                const float2 l1 = make_float2(mag * cs, mag * sn);
                const float inv = 1.f / (lr * lr + li * li);
                const float2 cf = cmul(make_float2(l1.x - 1.f, l1.y), make_float2(lr * inv, -li * inv));
                sts128u(sb + OFF_K + 16 * t, __float_as_uint(l1.x), __float_as_uint(P.swapB ? -l1.y : l1.y),
                        P.swapB ? pack2(-cf.y, cf.x) : pack2(cf.x, -cf.y), P.swapB ? pack2(-cf.x, -cf.y) : pack2(-cf.y, -cf.x));
                if (tid == 128) PROFX(92);
            }
            {
                const int kk = (t >> 3) & 7, r = t & 7;
                float sn, cs;
                sincospif((float)(((cls + 256 * kk) * r) & 2047) * (1.f / 1024.f), &sn, &cs);
                sn *= 1.f / 1024.f; cs *= 1.f / 1024.f;
                const uint32_t gf = sb + OFF_G + kk * 16 + r * 2, gi = sb + OFF_G + 512 + r * 16 + (kk & 1) * 128 + (kk & 6);
                if (t < 64) {
                    sts16(gf, cs); sts16(gf + 128, real_cls ? 0.f : sn); sts16(gf + 256, -sn); sts16(gf + 384, real_cls ? 0.f : cs);
                    sts16(gi, cs); sts16(gi + 8, -sn); sts16(gi + 256, sn); sts16(gi + 264, cs);
                }
            }
            if (main_cta) {
                load_fa(FA0, 16);
                if (t == 0) PROFX(91);
                const uint32_t ua = sb + OFF_U + (lane >> 4) * 4096 + (8 * w + (lane & 7)) * 128 + ((((lane >> 3) & 1) ^ (lane & 7)) << 4);
                float acc[4][32];
                const uint64_t db = make_desc(OFF_U, 8192, 1024);
                uint32_t x[4][8], y[4][8];
                float gp[4][4];
#pragma unroll
                for (int m = 0; m < 6; m++) {
                    if (m >= 2) {
                        const int n = m - 2;
                        if (m < 5) wgmma_wait<1>(); else wgmma_wait<0>();
#pragma unroll
                        for (int i = 0; i < 32; i++) asm volatile("" : "+f"(acc[n][i]) :: "memory");
                        asm volatile("" : "+f"(gp[n][0]), "+f"(gp[n][2]) :: "memory");
#pragma unroll
                        for (int j = 0; j < 8; j++) { x[n][j] = pack2(acc[n][4 * j], acc[n][4 * j + 1]); y[n][j] = pack2(acc[n][4 * j + 2], acc[n][4 * j + 3]); }
                    }
                    if (m < 4) {
                        mbar_wait(bars + 8 * (BAR_XC + m), 0);
                        if (t == 0 && m == 3) PROF(8);
                        wgmma_fence();
                        wgmma_rs_n64<0, 1>(acc[m], fa[4 * m], db + 512 * m);
#pragma unroll
                        for (int j = 1; j < 4; j++) wgmma_rs_n64<1, 1>(acc[m], fa[4 * m + j], db + 512 * m + 128 * j);
#pragma unroll
                        for (int j = 0; j < 4; j++) wgmma_n8(gp[m], make_desc(OFF_U, 16, 1024) + 512 * m + 2 * j, make_desc(OFF_GW, 16, 1024) + 2 * j, j);
                        wgmma_commit();
                    }
                }
                if (t < 4) {
#pragma unroll
                    for (int j = 0; j < 8; j++) {
                        const uint32_t s0 = bf_add2(x[0][j], x[2][j]), s2 = bf_add2(x[1][j], x[3][j]), ty = bf_sub2(y[1][j], y[3][j]), sy = bf_add2(y[1][j], y[3][j]);
                        const uint32_t b0 = y[0][j], b2 = y[2][j];
                        y[1][j] = bf_sub2(x[3][j], x[1][j]); x[1][j] = bf_sub2(x[0][j], x[2][j]);
                        x[0][j] = bf_add2(s0, s2); y[0][j] = bf_sub2(s0, s2);
                        x[2][j] = bf_add2(b0, ty); y[2][j] = bf_add2(sy, b2) ^ 0x80008000u;
                        x[3][j] = bf_sub2(b0, ty); y[3][j] = bf_sub2(b2, sy);
                    }
                } else {
#pragma unroll
                    for (int j = 0; j < 8; j++) {
                        const uint32_t s0x = bf_add2(x[0][j], x[2][j]), s1x = bf_sub2(x[0][j], x[2][j]), s2x = bf_add2(x[1][j], x[3][j]), tx = bf_sub2(x[1][j], x[3][j]);
                        const uint32_t s0y = bf_add2(y[0][j], y[2][j]), s1y = bf_sub2(y[0][j], y[2][j]), s2y = bf_add2(y[1][j], y[3][j]), ty = bf_sub2(y[1][j], y[3][j]);
                        x[0][j] = bf_add2(s0x, s2x); y[0][j] = bf_add2(s0y, s2y);
                        x[1][j] = bf_add2(s1x, ty); y[1][j] = bf_sub2(s1y, tx);
                        x[2][j] = bf_sub2(s0x, s2x); y[2][j] = bf_sub2(s0y, s2y);
                        x[3][j] = bf_sub2(s1x, ty); y[3][j] = bf_add2(s1y, tx);
                    }
                }
                helper_sync();
                if (q == 0) {
#pragma unroll
                    for (int i = 0; i < 2; i++)
                        sts128u(sb + OFF_GW + (16 * w + 8 * i + g) * 16, __float_as_uint(gp[0][2 * i]), __float_as_uint(gp[1][2 * i]), __float_as_uint(gp[2][2 * i]), __float_as_uint(gp[3][2 * i]));
                }
#pragma unroll
                for (int c = 0; c < 4; c++)
#pragma unroll
                    for (int j = 0; j < 8; j += 2) {
                        stsm_x4((ua ^ (j << 4)) + c * 8192, x[c][j], x[c][j + 1], y[c][j], y[c][j + 1]);
                        if (P_S1 && (j & 2)) pause(P_S1);
                    }
                if (t == 0) PROF(21);
            }
            __syncwarp();
            warp_arrive(bars + 8 * BAR_S1);
        }
        {
            float acc[2][64];
            float2 lam8[2], lam32[2], lam64[2], l32q[2], ex[2];
            float2 ag[2][4];
            asm volatile("{\n.reg .pred p;\nsetp.lt.u32 p, %0, 128;\n@p bar.sync 4, 384;\n}" :: "r"(tid) : "memory");
            if (main_cta) {
                ring_steps<0>(acc, sb, fb, 16, 5 - wg, wg * SLOT_OF(16), 0, 2 * wg, 2 + wg, 16 * wg);
                mbar_wait(bars + 8 * BAR_S1, 0);
                const uint4* ap = (const uint4*)kept(1) + (((tc - 1 - q) >> 2) * 2048 + (dt + 8 * wg) * 128 + t);
                const uint64_t k0 = kept(0);
                const uint32_t fl = (uint32_t)k0;
                uint32_t tag = ((uint32_t)(k0 >> 32) & 7) | 8;
                float2 lam1[2], la[2], lb[2], l2[2], l4[2], wq[2], w4[2];
                uint32_t m0[2], m1[2], kr[8], ki[8];
                auto weights = [&](int i) {
                    const float2 l128 = csq(lam64[i]), l256 = csq(l128), one = make_float2(1.f, 0.f);
                    w4[i] = csq(l256);
                    wq[i] = cmul(((tc - 1 - q) & 1) ? l128 : one, ((tc - 1 - q) & 2) ? l256 : one);
                    l32q[i] = cmul((q & 1) ? la[i] : one, (q & 2) ? lb[i] : one);
                    asm volatile("" : "+f"(w4[i].x), "+f"(w4[i].y), "+f"(wq[i].x), "+f"(wq[i].y), "+f"(l32q[i].x), "+f"(l32q[i].y));
                };
#pragma unroll
                for (int i = 0; i < 2; i++) {
                    const uint4 kv = lds128u(sb + OFF_K + (64 * wg + 32 * i + (t >> 2)) * 16);
                    lam1[i] = make_float2(__uint_as_float(kv.x), __uint_as_float(kv.y));
                    m0[i] = kv.z; m1[i] = kv.w;
                    l2[i] = csq(lam1[i]); l4[i] = csq(l2[i]); lam8[i] = csq(l4[i]);
                    lam32[i] = csq(csq(lam8[i])); lam64[i] = csq(lam32[i]);
                    la[i] = q >= 1 ? lam32[i] : make_float2(0.f, 0.f); lb[i] = q >= 2 ? lam64[i] : make_float2(0.f, 0.f);
                    asm volatile("" : "+f"(lam8[i].x), "+f"(lam8[i].y), "+f"(la[i].x), "+f"(la[i].y), "+f"(lb[i].x), "+f"(lb[i].y), "+f"(lam64[i].x), "+f"(lam64[i].y));
                    if (W_EARLY) weights(i);
                }
                kr[1] = pack2(l2[0].x, l2[1].x); ki[1] = pack2(l2[0].y, l2[1].y); kr[3] = pack2(l4[0].x, l4[1].x); ki[3] = pack2(l4[0].y, l4[1].y);
                asm volatile("" : "+r"(kr[1]), "+r"(ki[1]), "+r"(kr[3]), "+r"(ki[3]));
                uint32_t pub = q == 3 && tc < 15;
                const uint4* as = ap + (2045 + mq);
                asm volatile("" : "+l"(ap), "+l"(as), "+r"(tag), "+r"(pub));
                sched_fence();
                float2 v[2];
                wgmma_wait<1>();
#pragma unroll
                for (int o = 0; o < 64; o++) asm volatile("" : "+f"(acc[0][o]) :: "memory");
#pragma unroll
                for (int i = 0; i < 2; i++) {
#pragma unroll
                    for (int r = 1; r < 8; r++) {
#pragma unroll
                        for (int c = 0; c < 4; c++) {
                            const int o = 16 * c + 4 * (r >> 1) + (r & 1), u = 16 * c + 4 * ((r - 1) >> 1) + ((r - 1) & 1);
                            const float2 n = cfma(lam1[i], make_float2(acc[i][u], acc[i][u + 2]), make_float2(acc[i][o], acc[i][o + 2]));
                            acc[i][o] = n.x; acc[i][o + 2] = n.y;
                        }
                        if (!i && r == R_REL) {
#pragma unroll
                            for (int o = 0; o < 64; o++) asm volatile("" : "+f"(acc[0][o]));
                            sched_fence();
                            wgmma_wait_all(acc[1]);
                            warp_arrive(bars + 8 * (BAR_EMPTY + SLOT_OF(15)));
                            sched_fence();
                            if (tid == 0) PROF(3);
                            if (tid == 128) PROF(25);
                            if (tid == 224) PROFG(12);
                        }
                        if (i && r == R_MID) {
#pragma unroll
                            for (int o = 0; o < 64; o++) asm volatile("" : "+f"(acc[1][o]));
                            asm volatile("" : "+f"(v[0].x), "+f"(v[0].y));
                            sched_fence();
                        }
                    }
#pragma unroll
                    for (int c = 0; c < 4; c++) ag[i][c] = make_float2(acc[i][16 * c + 13], acc[i][16 * c + 15]);
                    v[i] = ag[i][0];
#pragma unroll
                    for (int c = 1; c < 4; c++) v[i] = cfma(lam8[i], v[i], ag[i][c]);
                    float2 n = make_float2(__shfl_up_sync(0xffffffffu, v[i].x, 1, 4), __shfl_up_sync(0xffffffffu, v[i].y, 1, 4));
                    v[i] = cfma(la[i], n, v[i]);
                    n = make_float2(__shfl_up_sync(0xffffffffu, v[i].x, 2, 4), __shfl_up_sync(0xffffffffu, v[i].y, 2, 4));
                    v[i] = cfma(lb[i], n, v[i]);
                }
                asm volatile("{\n.reg .b64 a, b;\n.reg .pred p;\nsetp.ne.u32 p, %5, 0;\nmov.b64 a, {%1, %2};\nmov.b64 b, {%3, %4};\n@p st.relaxed.gpu.global.v2.b64 [%0], {a, b};\n}"
                    :: "l"(as), "r"((__float_as_uint(v[0].x) & ~15u) | tag), "r"(__float_as_uint(v[0].y)),
                       "r"((__float_as_uint(v[1].x) & ~15u) | tag), "r"(__float_as_uint(v[1].y)), "r"(pub) : "memory");
                PROFS(72 + 8 * wg);
                sched_fence();
                uint4 rr[4];
                auto poll = [&]() {
#pragma unroll
                    for (int n = 0; n < 4; n++)
                        asm volatile("{\n.reg .b64 a, b;\n.reg .pred p;\nsetp.lt.s32 p, %5, %6;\ncvt.u64.u32 a, %7;\nmov.b64 b, a;\n"
                                     "@p ld.relaxed.gpu.global.v2.b64 {a, b}, [%4];\nmov.b64 {%0, %1}, a;\nmov.b64 {%2, %3}, b;\n}"
                            : "=r"(rr[n].x), "=r"(rr[n].y), "=r"(rr[n].z), "=r"(rr[n].w) : "l"(ap - 2048 * n), "r"(4 * n), "r"(tc - q), "r"(tag) : "memory");
                };
                uint32_t hp[2][32];
                auto scale = [&](int i, uint32_t& x, uint32_t& y) {
                    const uint32_t u = bf_fma2(lo2(m0[i]), x, bf_mul2(hi2(m0[i]), y));
                    y = bf_fma2(lo2(m1[i]), x, bf_mul2(hi2(m1[i]), y)); x = u;
                };
#pragma unroll
                for (int i = 0; i < 2; i++) {
                    ex[i] = make_float2(__shfl_up_sync(0xffffffffu, v[i].x, 1, 4), __shfl_up_sync(0xffffffffu, v[i].y, 1, 4));
#pragma unroll
                    for (int j = 0; j < 16; j++) {
                        const int o = 4 * (j >> 2) + 16 * (j & 1) + ((j >> 1) & 1), u = 8 * (j >> 2) + (j & 3);
                        hp[i][u] = pack2(acc[i][o], acc[i][o + 32]); hp[i][u + 4] = pack2(acc[i][o + 2], acc[i][o + 34]);
                    }
                    if (q == 0) ex[i] = make_float2(0.f, 0.f);
                }
                if (SEP) {
#pragma unroll
                    for (int j = 0; j < 64; j++) asm volatile("" : "+r"(hp[j >> 5][j & 31]));
                    sched_fence();
                }
#pragma unroll
                for (int j = 0; j < 32; j++) scale(j >> 4, hp[j >> 4][2 * (j & 12) + (j & 3)], hp[j >> 4][2 * (j & 12) + (j & 3) + 4]);
#pragma unroll
                for (int i = 0; i < 2; i++) {
#pragma unroll
                    for (int j = 0; j < 32; j++) asm volatile("" : "+r"(hp[i][j]));
                    asm volatile("" : "+f"(ex[i].x), "+f"(ex[i].y));
                }
                PROFS(73 + 8 * wg);
                mbar_wait(bars + 8 * (wg ? BAR_HD : BAR_EMPTY + 4), 0);
                if (wg) mbar_wait(bars + 8 * BAR_WR, 0);
                pause((wg ? P_CARB : P_CAR) + D_CAR * tc);
                poll();
                sched_fence();
                uint32_t hs = sb + OFF_HS + (lane >> 4) * 1024 + w * 256 + (lane & 7) * 32 + (((lane << 1) ^ (lane << 2)) & 16), hs1 = hs + 16384 + wg * 18432;
                asm volatile("" : "+r"(hs), "+r"(hs1));
                {
                    const uint32_t cj = (fl & 128) ? 0u : 0x80008000u;
                    kr[0] = pack2(lam1[0].x, lam1[1].x); ki[0] = pack2(lam1[0].y, lam1[1].y) ^ cj; kr[7] = pack2(lam8[0].x, lam8[1].x); ki[7] = pack2(lam8[0].y, lam8[1].y) ^ cj;
                    ki[1] ^= cj; ki[3] ^= cj;
                    kr[2] = kr[1]; ki[2] = ki[1]; cmul2(kr[2], ki[2], kr[0], ki[0]);
                    const uint32_t n4 = neg2(ki[3]);
#pragma unroll
                    for (int j = 0; j < 3; j++) { kr[4 + j] = kr[j]; ki[4 + j] = ki[j]; cmul2(kr[4 + j], ki[4 + j], kr[3], ki[3], n4); }
#pragma unroll
                    for (int j = 0; j < 8; j++) asm volatile("" : "+r"(kr[j]), "+r"(ki[j]));
                    if (!W_EARLY) { weights(0); weights(1); }
                }
                sched_fence();
                float2 pt[2];
                auto sum = [&]() {
                    uint32_t bad = 0;
#pragma unroll
                    for (int j = 0; j < 4; j++) bad |= (rr[j].x ^ tag) | (rr[j].z ^ tag);
#pragma unroll
                    for (int i = 0; i < 2; i++) {
                        auto val = [&](int n) { return make_float2(__uint_as_float(i ? rr[n].z : rr[n].x), __uint_as_float(i ? rr[n].w : rr[n].y)); };
                        pt[i] = cmul(wq[i], cfma(w4[i], cfma(w4[i], cfma(w4[i], val(3), val(2)), val(1)), val(0)));
                        asm volatile("" : "+f"(pt[i].x), "+f"(pt[i].y));
                    }
                    return __any_sync(0xffffffffu, bad & 15);
                };
                if (sum()) {
#pragma unroll 1
                    for (unsigned n = 0; n < SPIN_LIMIT; n++) {
                        if (n < 3) PROFS(74 + 8 * wg + n);
                        poll();
                        if (!sum()) break;
                    }
                }
#pragma unroll
                for (int i = 0; i < 2; i++) {
                    float2 part = pt[i];
                    part.x += __shfl_xor_sync(0xffffffffu, part.x, 1); part.y += __shfl_xor_sync(0xffffffffu, part.y, 1);
                    part.x += __shfl_xor_sync(0xffffffffu, part.x, 2); part.y += __shfl_xor_sync(0xffffffffu, part.y, 2);
                    ex[i] = cfma(l32q[i], part, ex[i]);
#pragma unroll
                    for (int c = 0; c < 4; c++) { const float2 e = cfma(lam8[i], ex[i], ag[i][c]); ag[i][c] = ex[i]; ex[i] = e; }
                }
                if (t == 0) PROF(4 + 25 * wg);
#pragma unroll
                for (int i = 0; i < 2; i++) {
                    uint32_t cr[2], ci[2], cn[2];
#pragma unroll
                    for (int c = 0; c < 2; c++) { cr[c] = pack2(ag[i][c].x, ag[i][c + 2].x); ci[c] = pack2(ag[i][c].y, ag[i][c + 2].y); scale(i, cr[c], ci[c]); cn[c] = ci[c] ^ 0x80008000u; }
#pragma unroll
                    for (int n = 0; n < 4; n++) {
                        uint32_t* h = &hp[i][16 * (n & 1) + 4 * (n >> 1)];
                        if (fl & (256 << (4 * i + n))) {
#pragma unroll
                            for (int j = 0; j < 8; j++) {
                                const uint32_t x = kr[4 * (n & 1) + (j >> 1)], y = ki[4 * (n & 1) + (j >> 1)];
                                uint32_t& d = h[j + (j & 4)];
                                d = bf_fma2(i ? hi2(x) : lo2(x), (n & 2) ? ci[j & 1] : cr[j & 1], bf_fma2(i ? hi2(y) : lo2(y), (n & 2) ? cr[j & 1] : cn[j & 1], d));
                            }
                        }
                        stsm_x4((i ? hs1 : hs) + n * 4096, h[0], h[1], h[2], h[3]);
                        stsm_x4((i ? hs1 : hs) + n * 4096 + 2048, h[8], h[9], h[10], h[11]);
                        if (4 * i + n == HS0 - 1 || 4 * i + n == 7) {
                            if (4 * i + n == 7 || HF) fence_proxy_async_smem();
                            __syncwarp();
                            warp_arrive(bars + 8 * (BAR_HW + (4 * i + n == 7)));
                        }
                        if (!i && !n && !wg) PROFS(77);
                    }
                }
                if (t == 0) PROF(5 + 25 * wg);
            } else {
                mbar_wait(bars + 8 * BAR_S1, 0);
            }
        }
        if (!main_cta) {
            if (wg) mbar_wait(bars + 8 * BAR_WR, 0);
            fence_proxy_async_smem();
        }
#pragma unroll 1
        for (int ps = wg; ps < 1 + 2 * wg; ps++) {
            if (ps != 1) {
                if (!ps) mbar_wait(bars + 8 * BAR_U, 0);
                if (t == 0) PROF(ps ? 7 : 23);
                radix8(sb, ps, w, lane, 5 + wg);
                if (t == 0) PROF(ps ? 24 : 22);
                if (ps) break;
                bar_sync(5, 128);
                if (FPOS & 1) fence_proxy_async_smem();
            }
            mbar_wait(bars + 8 * (BAR_C + ps), 0);
            phase_c(sb, ps, b + ps == 0, w, lane);
        }
        if (wg == 0) {
            __syncwarp();
            warp_arrive(bars + 8 * BAR_WR);
            if (main_cta) {
                float acc[2][64];
                ring_steps<1>(acc, sb, bars + 8 * BAR_FULL, 31 - LEAD, NS, SLOT_OF(32), 1, 3, 0, 32);
                auto full = [&](int k) { mbar_wait(bars + 8 * (BAR_FULL + SLOT_OF(k)), k > 62); PROFT(k); };
                constexpr int HL = VK == 64 ? 63 : 65;
                auto hstep = [&](int k, int i) {
                    const uint64_t da = make_desc(SLOT_OF(k) * SLOT + i * 8192, 2048, 256, 3), db = make_desc(SLOT_OF(k) * SLOT + 16384, 16, 1024);
                    if (!(LEAD && i && k == HL)) wgmma_fence();
#pragma unroll
                    for (int j = 0; j < 4; j++) wgmma_n128<1, 0>(acc[i], da + 32 * j, db + 2 * j, 1);
                };
                auto vstep = [&](int k, int i) {
                    const uint64_t da = make_desc(OFF_U - i * 32768 + k * 8192, 16, 1024), db = make_desc(SLOT_OF(VK + (k >> 1)) * SLOT + (k & 1) * 16384, 8192, 1024);
                    if (k || !i || LEAD) wgmma_fence();
#pragma unroll
                    for (int j = 0; j < 4; j++) wgmma_n128<0, 1>(acc[i], da + 2 * j, db + 128 * j, 1);
                };
                __syncwarp();
                if (LEAD) {
                    full(62);
                    hstep(62, 0);
                    wgmma_commit();
                    wgmma_wait<1>();
                    warp_arrive(bars + 8 * (BAR_EMPTY + SLOT_OF(61)));
                }
                if (VK == 64) {
                    full(63);
                    hstep(63, 0);
                }
                bar_sync(4, 256);
                full(VK);
                vstep(0, 0);
                vstep(1, 0);
                if (VK == 63) {
                    full(64);
                    vstep(2, 0);
                    vstep(3, 0);
                }
                const CUtensorMap* maps = (const CUtensorMap*)kept(3);
                const uint32_t ob = sb + OFF_U + w * 2048, oa = ob + g * 256 + (((q >> 1) ^ (2 * g & 6)) << 4) + (q & 1) * 8;
#pragma unroll
                for (int i = 0; i < 2; i++) {
                    uint4 e[8];
                    const uint2 sc = lds64u(sb + OFF_SC + (64 * i + 16 * w + 2 * g) * 4);
                    bar_sync(8 + i, 256);
#pragma unroll
                    for (int j = 0; j < 8; j++) e[j] = lds128u(sb + OFF_HS + i * 16384 + (j >> 2) * 8192 + w * 2048 + (j & 3) * 512 + lane * 16);
                    if (i) wgmma_wait<0>();
                    else {
                        full(65);
                        if (VK == 64) {
                            vstep(2, 0);
                            vstep(3, 0);
                        } else hstep(65, 0);
                        wgmma_commit();
                        if (LEAD) hstep(62, 1);
                        hstep(HL, 1);
                        if (!LEAD) vstep(0, 1);
                        wgmma_commit();
                        wgmma_wait<1>();
                    }
#pragma unroll
                    for (int o = 0; o < 64; o++) asm volatile("" : "+f"(acc[i][o]) :: "memory");
                    if (tid == 0) PROF(17 + i);
                    if (tid == 96 && i) PROFG(20);
#pragma unroll
                    for (int c = 0; c < 4; c++) {
#pragma unroll
                        for (int j = 0; j < 8; j++) {
                            const int o = 16 * c + 2 * j;
                            const uint4 e4 = e[2 * c + (j >> 2)];
                            const uint32_t ev = (j & 2) ? ((j & 1) ? e4.w : e4.z) : ((j & 1) ? e4.y : e4.x);
                            const float f = __uint_as_float((j & 1) ? sc.y : sc.x);
                            sts64((oa ^ ((j >> 1) << 5) ^ ((j & 1) * 144)) + c * 8192 - i * 32768, fmaf(f, acc[i][o], bf_lo(ev)), fmaf(f, acc[i][o + 1], bf_hi(ev)));
                        }
                        if (!i && c >= VFIRST && c < 3 + LEAD) {
                            vstep(c + 1 - LEAD, 1);
                            if (c == 2 + LEAD) wgmma_commit();
                        }
                        fence_proxy_async_smem();
                        __syncwarp();
                        if (elect()) tma_store_3d(maps + 9, ob + c * 8192 - i * 32768, 128 * dt + 32 * c, 128 * (tc & 1) + 64 * i + 16 * w, tc >> 1);
                        __syncwarp();
                        if (!i && c < VFIRST && c < 3 + LEAD) {
                            vstep(c + 1 - LEAD, 1);
                            if (c == 2 + LEAD) wgmma_commit();
                        }
                    }
                }
                if (elect()) {
                    bulk_commit();
                    bulk_wait_read();
                }
                if (tid == 0) PROF(19);
                if (tid == 96) { PROF(20); PROFG(4); }
            }
        } else {
            __syncwarp();
            if (tid == 224) PROFG(16);
            if (main_cta) {
                float gs[16];
                uint32_t dk[16], tv[4][4];
#pragma unroll
                for (int j = 0; j < 16; j++) gs[j] = __ldcg(g_gp + (16 * (tc >> 1) + j) * 256 + 128 * (tc & 1) + t);
#pragma unroll
                for (int j = 0; j < 16; j++) dk[j] = ldg32u(P.dskip + 128 * dt + 8 * j + 2 * q);
                const int m0 = ((t >> 2) & 14) + (t >> 6), c0 = 4 * ((t ^ (t >> 3)) & 7);
#pragma unroll
                for (int j = 0; j < 16; j++) {
                    const float a = (float)((j & 3) || c0 ? c0 + (j & 3) : -96) * ((float)(128 * (tc & 1) + 4 * (j & 12) + m0) * 0.024543692606170260f);
                    tv[j >> 2][j & 3] = pack2(__cosf(a), -__sinf(a));
                }
#pragma unroll
                for (int j = 0; j < 4; j++) gs[j] = (gs[j] + gs[j + 4]) + (gs[j + 8] + gs[j + 12]);
                gs[0] = (gs[0] + gs[1]) + (gs[2] + gs[3]);
                const float gg = bf_round(__fdividef(1.f, 1.f + __expf(-bf_round(gs[0])))), og = bf_round(1.f - gg), o2 = fmaxf(2.f * og, 0x1p-40f);
                sts32(sb + OFF_SC + 4 * t, __float_as_uint(o2));
                sts32(sb + OFF_SC + 512 + 4 * t, pack2(__fdividef(gg, o2), og));
                bar_sync(6, 128);
                if (t == 0) PROFX(95);
                auto sign = [](uint32_t n) { return (((n + 1) & 2) << 30) | ((n & 2) << 14); };
                const uint32_t sel = (t & 64) ? 0x1032 : 0x3210;
#pragma unroll
                for (int e = 1; e >= 0; e--) {
                    uint32_t f[4];
#pragma unroll
                    for (int j = 0; j < 4; j++) f[j] = lds16(sb + OFF_SC + 512 + (64 * e + 16 * j + m0) * 4) * 0x10001u;
                    mbar_wait(bars + 8 * (e ? BAR_HD + 1 : BAR_U), !e);
#pragma unroll
                    for (int j = 0; j < 16; j++) {
                        const int k = j & 3, r = j >> 2;
                        uint32_t o[4];
#pragma unroll
                        for (int u = 0; u < 4; u++) {
                            uint32_t v = tv[r][u];
                            if (u == 0 && k < 2 && !c0) v = k ? 0x3f80u : 0x3f003f00u | (t & 64) << 25;
                            if (e) v = ((u & 1) ? __byte_perm(v, 0, 0x1032) : v) ^ sign(u);
                            o[u] = bf_mul2((k & 1) ? __byte_perm(v, 0, sel) : v, f[r] ^ sign(k * m0));
                        }
                        sts128u(sb + OFF_U - e * 32768 + (4 * k + r) * 2048 + t * 16, o[0], o[1], o[2], o[3]);
                        if (P_T && (j & N_T) == N_T) pause(P_T);
                    }
                }
                fence_proxy_async_smem();
                bar_arrive(4, 256);
                if (t == 0) PROF(16);
                const uint32_t xa = sb + OFF_HS + (16 * w + (lane & 15)) * 128 + (((lane >> 4) ^ (lane & 7)) << 4);
#pragma unroll
                for (int e = 0; e < 2; e++) {
                    const uint2 u = lds64u(sb + OFF_SC + 512 + (64 * e + 16 * w + 2 * g) * 4);
                    const uint32_t o0 = __byte_perm(u.x, 0, 0x3232), o1 = __byte_perm(u.y, 0, 0x3232);
                    uint32_t x[8][4];
                    mbar_wait(bars + 8 * (BAR_W + e), 1);
#pragma unroll
                    for (int j = 0; j < 8; j++) {
                        ldsm_x4(x[j], (xa ^ ((j & 3) << 5)) + e * 16384 + (j >> 2) * 8192);
                        if (P_SK && (j & 1)) pause(P_SK);
                    }
#pragma unroll
                    for (int j = 0; j < 8; j++) {
#pragma unroll
                        for (int c = 0; c < 4; c++) x[j][c] = bf_mul2(bf_mul2(x[j][c], dk[2 * j + (c >> 1)]), (c & 1) ? o1 : o0);
                        sts128u(sb + OFF_HS + e * 16384 + (j >> 2) * 8192 + w * 2048 + (j & 3) * 512 + lane * 16, x[j][0], x[j][1], x[j][2], x[j][3]);
                        if (P_SK && (j & 1)) pause(P_SK);
                    }
                    bar_arrive(8 + e, 256);
                    if (t == 0 && !e) PROF(15);
                }
            }
            if (t == 0) {
                const unsigned old = atomicAdd(&g_cnt[CNT_DONE * CS], 1u);
                if (old == 128)
                    asm volatile("st.global.u32 [%0], 0;\nst.global.u32 [%0 + %2], %1;" :: "l"(&g_cnt[CNT_DONE * CS]), "r"((uint32_t)(kept(0) >> 32)), "n"((CNT_EPOCH - CNT_DONE) * CS * 4) : "memory");
            }
        }
    } else {
        const int w = warp - 8;
        if (w == 0) {
            bar_sync(7, 64);
            if (!main_cta || !elect()) return;
            {
                int s = 0; uint32_t ph = 0;
#pragma unroll 1
                for (int k = 5; k < 32; k++) {
                    asm volatile(WAIT_LOOP
                        "cp.async.bulk.tensor.4d.shared::cluster.global.mbarrier::complete_tx::bytes [%3], [%5, {%7, %10, %10, %8}], [%2];\n"
                        "cp.async.bulk.tensor.4d.shared::cluster.global.mbarrier::complete_tx::bytes [%4], [%6, {%7, %10, %10, %9}], [%2];\n"
                        "mbarrier.arrive.expect_tx.shared::cta.b64 _, [%2], 32768;\n}"
                        :: "r"(bars + 8 * (BAR_EMPTY + s)), "r"(ph), "r"(bars + 8 * (BAR_FULL + s + (k >> 4) * 5)), "r"(sb + s * SLOT + 16384), "r"(sb + s * SLOT),
                           "l"(&mapX), "l"(&mapB), "r"((k & 15) * 64), "r"(tc * 64), "r"(dt * 8 + (k >> 4) * 64), "r"(0) : "memory");
                    PROFR(k < 19 ? k - 5 : k - 4);
                    if (++s == (k < 15 ? 5 : NS)) { s = 0; ph ^= 1; }
                }
                auto load_x = [&](int e) {
                    mbar_expect_tx(bars + 8 * (BAR_W + e), 16384);
#pragma unroll
                    for (int i = 0; i < 2; i++) tma_load_5d(sb + OFF_HS + e * 16384 + i * 8192, &mapXe, bars + 8 * (BAR_W + e), 128 * dt + 64 * i, 8 * (tc & 1) + 4 * e, tc >> 1);
                };
                const uint8_t* hp = g_hT + tc * 16384;
                auto load_h = [&](int h) {
                    asm volatile("{\n.reg .pred q;\n.reg .u32 v, m;\nld.volatile.shared.u32 v, [%10];\nsetp.gt.u32 q, v, %8;\nmov.u32 m, 0;\n" WAIT_LOOP
                        "cp.async.bulk.tensor.3d.shared::cluster.global.mbarrier::complete_tx::bytes [%3], [%5, {%9, %7, %8}], [%2];\n"
                        "@q bra LH;\nLV:\nld.volatile.shared.u32 v, [%10];\nadd.u32 m, m, 1;\nsetp.le.u32 q, v, %8;\nsetp.lt.and.u32 q, m, 4194304, q;\n@q bra LV;\nLH:\n"
                        "cp.async.bulk.shared::cluster.global.mbarrier::complete_tx::bytes [%4], [%6], 16384, [%2];\n"
                        "mbarrier.arrive.expect_tx.shared::cta.b64 _, [%2], 32768;\n}\n}"
                        :: "r"(bars + 8 * (BAR_EMPTY + s)), "r"(ph), "r"(bars + 8 * (BAR_FULL + s)), "r"(sb + s * SLOT + 16384), "r"(sb + s * SLOT),
                           "l"(&mapCre + (h & 1)), "l"(hp), "r"(dt * 128), "r"(h >> 1), "r"(0), "r"(sb + OFF_KEPT + 32) : "memory");
                    PROFR(h + (h < VK - 32 ? 28 : 30));
                    hp += 16 * 16384;
                    if (h == K_XE - 32) load_x(0);
                    if (++s == NS) { s = 0; ph ^= 1; }
                };
#pragma unroll 1
                for (int h = 0; h < VK - 32; h++) load_h(h);
                {
                        mbar_wait(bars + 8 * (BAR_F + 2), 0);
#pragma unroll
                        for (int i = 0; i < 2; i++) {
                            const uint32_t pb = bars + 8 * (BAR_XC + i), full = bars + 8 * (BAR_FULL + SLOT_OF(VK + i)), st = sb + SLOT_OF(VK + i) * SLOT;
                            uint32_t rb;
                            asm("mapa.shared::cluster.u32 %0, %1, %2;" : "=r"(rb) : "r"(pb), "r"(~b & 1));
                            asm volatile(WAIT_LOOP "mbarrier.arrive.shared::cluster.b64 _, [%2];\n}" :: "r"(bars + 8 * (BAR_EMPTY + SLOT_OF(VK + i))), "r"(ph), "r"(rb) : "memory");
                            asm volatile(WAIT_LOOP "cp.async.bulk.tensor.3d.shared::cluster.global.mbarrier::complete_tx::bytes.multicast::cluster [%2], [%3, {%5, %6, %7}], [%4], %8;\n}"
                                :: "r"(pb), "r"(1), "r"(st + (b & 1) * 16384), "l"(&mapV), "r"(full), "r"(0), "r"(i * 128 + (b & 1) * 64), "r"((tc >> 1) * 16 + dt * 2), "h"((uint16_t)3) : "memory");
                            mbar_expect_tx(full, SLOT);
                            PROFR(VK - 4 + i);
                        }
                    }
                if (VK == 63) { s = SLOT_OF(65); load_h(31); }
                load_x(1);
            }
        } else {
            const unsigned epoch = load_epoch();
            bar_sync(0, 256);
            if (w == 1) {
                bar_arrive(7, 64);
                if (!elect()) return;
                {
                    if (main_cta) {
                        pause(T_XS);
                        bulk_load(sb + OFF_GW, P.gate_w + (b & 15) * 64, 128, bars + 8 * BAR_XC);
#pragma unroll 1
                        for (int c = 0; c < 4; c++) {
                            mbar_expect_tx(bars + 8 * (BAR_XC + c), c ? 8192 : 8192 + 128);
                            tma_load_4d(sb + OFF_U + c * 8192, &mapXs, bars + 8 * (BAR_XC + c), (b & 15) * 64, 0, c, b >> 4);
                            pause(P_XS);
                        }
                    }
                    mbar_wait(bars + 8 * BAR_S1, 0);
                    fence_proxy_async_smem();
                    if (main_cta) {
#pragma unroll 1
                        for (int c = 0; c < 4 * UN; c++) {
                            if (c) pause(PACE_U);
                            tma_store_4d(&mapU0, sb + OFF_U + c * (8192 / UN), (b & 15) * 64, UN == 4 ? 32 * (c >> 2) + 16 * (c & 1) : 32 * (c / UN), UN == 4 ? (c >> 1) & 1 : c % UN, b >> 4);
                        }
                        bulk_store(g_gp + b * 256, sb + OFF_GW, 1024);
                        bulk_commit();
                        bulk_wait0();
                        signal_counter(&g_cnt[CNT_U * CS]);
                    }
                    PROF(9);
                    mbar_expect_tx(bars + 8 * BAR_U, 32768);
                    wait_counter(&g_cnt[CNT_U * CS + (b & (NREP - 1)) * RS], epoch * 128);
                    PROF(11);
#pragma unroll
                    for (int i = 0; i < 8; i++) {
                        if (PACE_L && i && !(i & 1)) pause(PACE_L);
                        tma_load_4d(sb + OFF_U + i * 4096, &mapU2, bars + 8 * BAR_U, 0, 0, (i & 3) * 4, b == 128 ? 1 : b == 0 ? 0 : 2 * b + (i >> 2));
                    }
                    if (main_cta) {
#pragma unroll 1
                        for (int i = 0; i < 2; i++) {
#pragma unroll 1
                            for (int j = 0; j < 2 * HN; j++) {
                                const int hf = j / HN, jj = j % HN;
                                if (j) pause(i ? PACE_HB : PACE_HA);
                                if (j == 0 || j == HS0 * HN / 4) mbar_wait(bars + 8 * (BAR_HW + (j > 0)), i);
                                if (j == 0 && !HF) fence_proxy_async_smem();
                                tma_store_3d(&mapH, sb + OFF_HS + hf * (16384 + i * 18432) + jj * (16384 / HN), 0, 2 * tc + hf, (dt + 8 * i) * 16 + jj * (16 / HN));
                            }
                            bulk_commit();
                            bulk_wait0();
#pragma unroll
                            for (int r = 0; r < NREPH; r++)
                                asm volatile("red.relaxed.gpu.global.add.u64 [%0], %1;" :: "l"(&g_cnt[(CNT_H + 2 * i + (tc >> 3)) * CS + r * RS]), "l"(1ull << (8 * dt)) : "memory");
                            mbar_arrive(bars + 8 * (BAR_HD + i));
                            PROF(i ? 6 : 26);
                            const unsigned* cp = &g_cnt[(CNT_H + 2 * i + (tc & 1)) * CS + ((b >> 1) & (NREPH - 1)) * RS];
#pragma unroll 1
                            for (unsigned n = 0; n < SPIN_LIMIT; n++) {
                                uint64_t v;
                                asm volatile("ld.relaxed.gpu.global.u64 %0, [%1];" : "=l"(v) : "l"(cp) : "memory");
                                v = epoch * 0x0808080808080808ull - v;
                                sts32(sb + OFF_KEPT + 32, (__clzll(__brevll(v)) >> 3) + 8 * i);
                                if (!v) break;
                                if (P_HP) pause(P_HP);
                            }
                            PROF(1 + i);
                        }
                    }
                }
            } else {
                const int ld = (1026 * cls) >> 7, lm = (1026 * ((256 - cls) & 255)) >> 7;
                if (elect() && main_cta) {
                    if (w == 3) {
                        pause(T_W);
#pragma unroll 1
                        for (int i = 0; i < 8; i++) {
                            tma_prefetch_4d(&mapWr + (i & 1), 0, (i & 2) ? lm : ld, i >> 2, 0);
                            pause(200);
                        }
                    } else {
                        pause(T_BA + D_XS * tc);
                        if (tc > 4) tma_prefetch_4d(&mapB, tc * 64, 0, 0, dt * 8);
                        pause(T_B2);
                        bulk_prefetch_l2(((b & 1) ? P.b_im : P.b_re) + (64 + (b >> 1)) * 8192, 16384);
                        pause(T_W0 - D_XS * tc);
                    }
                }
#pragma unroll 1
                for (int ps = 0; ps < 2; ps++) {
                    const uint32_t wb = sb + OFF_W + (1 - ps) * 18432;
                    if (w == 2 && elect()) {
                        const uint32_t bw = bars + 8 * (BAR_W + ps);
                        if (ps && main_cta) mbar_wait(bars + 8 * BAR_HD, 0);
                        mbar_expect_tx(bw, ps ? 18432 : 18432 + 8192);
#pragma unroll 1
                        for (int i = 0; i < 4; i++) {
                            tma_load_4d(wb + (i >> 1) * 4608 + (i & 1) * 9216, &mapWr + (i & 1), bw, 0, i < 2 ? ld : lm, (i < 2 || b == 0) ? ps : 1 - ps, 0);
                            pause(P_W);
                        }
                        if (!ps) bulk_load(sb + OFF_F, c_tab + 8192, 8192, bw);
                        PROFX(85 + ps);
                    }
                    if (w == 3 && ps && main_cta && elect()) {
#pragma unroll 1
                        for (int i = 0; i < 8; i++) {
                            bulk_prefetch_l2(((b & 1) ? P.c_im : P.c_re) + (size_t)(b >> 1) * 16384 + i * 2048, 4096);
                            pause(P_C);
                        }
                    }
                    __syncwarp();
                    mbar_wait(bars + 8 * (BAR_W + ps), 0);
                    if (tid == 320) PROF(ps ? 31 : 10);
#pragma unroll 1
                    for (int u = 0; u < 4; u++) {
                        const int row = 2 * (w - 2) + (u >> 1), pl = u & 1;
                        const uint32_t dp = wb + pl * 9216 + row * 1152, mp = wb + pl * 9216 + 4608 + ((b == 0 && ps == 0) ? (4 - row) & 3 : 3 - row) * 1152;
                        const uint32_t od = dp + ((1026 * cls) & 127), om = mp + ((1026 * (256 - cls)) & 127);
                        uint32_t v[4][8], o[4][4];
#pragma unroll
                        for (int i = 0; i < 8; i++) {
                            const uint4 r = lds128u((i < 4 ? (od & ~15u) + 16 * lane + (i >> 1) * 512 : ((om + 1010) & ~15u) - 16 * lane - ((i >> 1) & 1) * 512) + (i & 1) * 16);
                            uint32_t* d = &v[i >> 1][4 * (i & 1)];
                            d[0] = r.x; d[1] = r.y; d[2] = r.z; d[3] = r.w;
                            if ((P_W0 || P_W1) && (i & 1) && i < 7) pause(ps ? P_W1 : P_W0);
                        }
                        const uint32_t e0 = lds16(om), e1 = lds16(od + 1024);
                        auto fwd = [&](int ws) {
#pragma unroll
                            for (int k = 0; k < 8; k++) o[k >> 2][k & 3] = __byte_perm(v[k >> 2][ws + (k & 3)], v[k >> 2][ws + (k & 3) + 1], (cls & 1) ? 0x5432 : 0x3210);
                        };
                        auto mir = [&](int ws) {
#pragma unroll
                            for (int k = 8; k < 16; k++) o[k >> 2][k & 3] = __byte_perm(v[k >> 2][ws + 3 - (k & 3)], v[k >> 2][ws + 4 - (k & 3)], (cls & 1) ? 0x1032 : 0x3254);
                        };
                        switch ((cls >> 1) & 3) { case 0: fwd(0); break; case 1: fwd(1); break; case 2: fwd(2); break; default: fwd(3); }
                        switch (((1 - cls) >> 1) & 3) { case 0: mir(0); break; case 1: mir(1); break; case 2: mir(2); break; default: mir(3); }
                        if (lane == 0) {
                            o[0][0] = pack2(fmaf(pl ? -0.5f : 0.5f, bf_lo(e0), 0.5f * bf_lo(o[0][0])), bf_hi(o[0][0]));
                            o[2][0] = pack2(fmaf(pl ? -0.5f : 0.5f, bf_lo(e1), 0.5f * bf_lo(o[2][0])), bf_hi(o[2][0]));
                        }
                        __syncwarp();
#pragma unroll
                        for (int i = 0; i < 4; i++)
                        {
                            sts128u((i < 2 ? dp : mp) + (i & 1) * 512 + ((lane * 16) ^ ((lane << 1) & 48)), o[i][0], o[i][1], o[i][2], o[i][3]);
                            if ((P_W0 || P_W1) && (i & 1)) pause(ps ? P_W1 : P_W0);
                        }
                    }
                    if (ps) fence_proxy_async_smem();
                    mbar_arrive(bars + 8 * (BAR_C + ps));
                    if (tid == 320) PROF(ps ? 12 : 28);
                }
                if (!elect()) return;
                if (w == 2) {
                    {
#pragma unroll 1
                        for (int i = 0; i < 8; i++) {
                            if (!(i & 3)) { mbar_wait(bars + 8 * BAR_VW, i >> 2); if (!i && !HF) fence_proxy_async_smem(); }
                            else pause(PACE_V);
                            if (!(real_cls && (i & 1))) tma_store_4d(&mapU2, sb + OFF_U + (i & 1) * 16384 + (i >> 1) * 4096, 0, 0, (i >> 1) * 4, b == 128 ? 1 : 2 * b + (i & 1));
                        }
                        bulk_commit();
                        bulk_wait_read();
                        mbar_arrive(bars + 8 * BAR_U);
                        bulk_wait0();
                        signal_counter(&g_cnt[CNT_V * CS]);
                        PROF(13);
                        if (main_cta) {
                            wait_counter(&g_cnt[CNT_V * CS + (b & (NREP - 1)) * RS], epoch * 129);
                            mbar_arrive(bars + 8 * (BAR_F + 2));
                            PROF(14);
                        }
                    }
                }
            }
        }
    }
}

typedef CUresult (*PFN_encodeTiled)(CUtensorMap*, CUtensorMapDataType, cuuint32_t, void*, const cuuint64_t*, const cuuint64_t*,
                                    const cuuint32_t*, const cuuint32_t*, CUtensorMapInterleave, CUtensorMapSwizzle,
                                    CUtensorMapL2promotion, CUtensorMapFloatOOBfill);

static CUtensorMap make_map(PFN_encodeTiled enc, const void* ptr, int rank, const cuuint64_t* dims, const cuuint64_t* strides, const cuuint32_t* box,
                            CUtensorMapSwizzle sw = CU_TENSOR_MAP_SWIZZLE_128B, CUtensorMapDataType dt = CU_TENSOR_MAP_DATA_TYPE_BFLOAT16) {
    CUtensorMap m;
    cuuint32_t es[5] = {1, 1, 1, 1, 1};
    enc(&m, dt, rank, (void*)ptr, dims, strides, box, es, CU_TENSOR_MAP_INTERLEAVE_NONE,
        sw, CU_TENSOR_MAP_L2_PROMOTION_L2_128B, CU_TENSOR_MAP_FLOAT_OOB_FILL_NONE);
    return m;
}

extern "C" void kernel_launch(void* const* d_in, const int* in_sizes, int n_in, void* d_out, int out_size) {
    const bf16* x = (const bf16*)d_in[0];
    const bf16* wr = (const bf16*)d_in[1];
    const bf16* wi = (const bf16*)d_in[2];
    const bf16* Bre = (const bf16*)d_in[6];
    const bf16* Bim = (const bf16*)d_in[7];
    const bf16* Cre = (const bf16*)d_in[8];
    const bf16* Cim = (const bf16*)d_in[9];

    void* fn = nullptr;
    cudaDriverEntryPointQueryResult st;
    cudaGetDriverEntryPoint("cuTensorMapEncodeTiled", &fn, cudaEnableDefault, &st);
    PFN_encodeTiled enc = (PFN_encodeTiled)fn;
    void *p_hT, *p_U;
    cudaGetSymbolAddress(&p_hT, g_hT);
    cudaGetSymbolAddress(&p_U, g_U);

    Params P;
    P.lam_re = (const bf16*)d_in[4]; P.lam_im = (const bf16*)d_in[5]; P.log_dt = (const bf16*)d_in[10];
    P.dskip = (const bf16*)d_in[11]; P.gate_w = (const bf16*)d_in[12]; P.c_re = Cre; P.c_im = Cim; P.b_re = Bre; P.b_im = Bim; P.x = x;
    P.swapB = Bim < Bre;
    for (int i = 0; i < 130; i++) {
        const int cl = i >> 1;
        const int role = cl < 4 ? 32 + 8 * cl : cl < 36 ? ((cl - 4) & 24) + ((cl - 5) & 7) : cl < 64 ? 33 + 8 * ((cl - 36) / 7) + (cl - 30) % 7 : cl;
        const int b = role * 2 + (i & 1), dt = ((b >> 1) & 4) + (b >> 5), tc = 4 * ((b >> 1) & 3) + ((b >> 3) & 2) + (b & 1);
        P.tile[i] = b < 128 ? make_int2(dt * 8, tc * 64) : make_int2(INT_MIN, (b & 1) * 64);
    }

    CUtensorMap mB, mX, mCre, mCim, mXs, mU0, mV, mU2, mXe, mO, mWr, mWi, mH;
    {
        cuuint64_t d[4] = {64, 2052, 2, 4}, s[3] = {128, 262656, 525312};
        cuuint32_t bx[4] = {64, 9, 1, 4};
        mWr = make_map(enc, wr, 4, d, s, bx, CU_TENSOR_MAP_SWIZZLE_NONE);
        mWi = make_map(enc, wi, 4, d, s, bx, CU_TENSOR_MAP_SWIZZLE_NONE);
    }
    {
        cuuint64_t d[3] = {128, 32, 256}, s[2] = {1024, 32768};
        cuuint32_t bx[3] = {128, 1, 16 / HN};
        mH = make_map(enc, p_hT, 3, d, s, bx, CU_TENSOR_MAP_SWIZZLE_NONE, CU_TENSOR_MAP_DATA_TYPE_UINT64);
    }
    {
        const bf16* lo = P.swapB ? Bim : Bre; const bf16* hi = P.swapB ? Bre : Bim;
        cuuint64_t d[4] = {1024, 8, 2, 128}, s[3] = {2048, (cuuint64_t)((const char*)hi - (const char*)lo), 16384};
        cuuint32_t bx[4] = {64, 8, 2, 8};
        mB = make_map(enc, lo, 4, d, s, bx);
    }
    {
        cuuint64_t d[4] = {1024, 2, 4, 976}, s[3] = {2048, 32 * 2048, 2 * 2048};
        cuuint32_t bx[4] = {64, 2, 4, 16};
        mX = make_map(enc, x, 4, d, s, bx);
    }
    {
        cuuint64_t d[3] = {64, 1024, 16}, s[2] = {2048, 128};
        cuuint32_t bx[3] = {64, 128, 1};
        mCre = make_map(enc, Cre, 3, d, s, bx);
        mCim = make_map(enc, Cim, 3, d, s, bx);
    }
    {
        cuuint64_t d[3] = {64, 256, 128}, s[2] = {16384, 128};
        cuuint32_t bx[3] = {64, 64, 2};
        mV = make_map(enc, p_U, 3, d, s, bx);
    }
    {
        cuuint64_t d[5] = {1024, 8, 2, 16, 8}, s[4] = {16 * 2048, 8 * 2048, 128 * 2048, 2048};
        cuuint32_t bx[5] = {64, 8, 2, 4, 1};
        mXe = make_map(enc, x, 5, d, s, bx);
    }
    {
        cuuint64_t d[3] = {1024, 256, 8}, s[2] = {8 * 4096, 4096};
        cuuint32_t bx[3] = {32, 16, 1};
        mO = make_map(enc, d_out, 3, d, s, bx, CU_TENSOR_MAP_SWIZZLE_128B, CU_TENSOR_MAP_DATA_TYPE_FLOAT32);
    }
    {
        cuuint64_t d[4] = {1024, 64, 4, 8}, s[3] = {32 * 2048, 8 * 2048, 2048};
        cuuint32_t bx[4] = {64, 64, 1, 1};
        mXs = make_map(enc, x, 4, d, s, bx);
    }
    {
        cuuint64_t d[4] = {1024, 128, 2, 8}, s[3] = {32768, 16384, 2048};
        cuuint32_t bx[4] = {64, UN == 4 ? 16 : 32, UN == 1 ? 2 : 1, 1};
        mU0 = make_map(enc, p_U, 4, d, s, bx);
    }
    {
        cuuint64_t d[4] = {64, 8, 16, 256}, s[3] = {2048, 128, 16384};
        cuuint32_t bx[4] = {64, 8, 4, 1};
        mU2 = make_map(enc, p_U, 4, d, s, bx);
    }
    cudaFuncSetAttribute(fused_kernel, cudaFuncAttributeMaxDynamicSharedMemorySize, SMEM_BYTES);
    fused_kernel<<<130, 384, SMEM_BYTES, cudaStreamPerThread>>>(mB, mX, mXs, mU0, mU2, mXe, mCre, mCim, mV, mO, mWr, mWi, mH, P);
}
```
